```python
import torch

def _softmax(x, axis=-1):
    return torch.softmax(x, dim=axis)
def _gelu(x):
    return torch.nn.functional.gelu(x, approximate="tanh")
def _silu(x):
    return torch.nn.functional.silu(x)
def _sigmoid(x):
    return torch.sigmoid(x)
def _layernorm(x, axis=-1, eps=1e-5):
    m = x.mean(dim=axis, keepdim=True)
    v = x.var(dim=axis, keepdim=True, unbiased=False)
    return (x - m) / torch.sqrt(v + eps)
def _scatter_add(tgt, idx, src, axis=0):
    return tgt.clone().index_add_(axis, idx, src)
def _segment_sum(src, seg, n):
    out = torch.zeros((n,) + src.shape[1:], dtype=src.dtype)
    return out.index_add_(0, seg, src)
def _pad(x, pw):
    flat = tuple(v for pair in reversed(pw) for v in pair)
    return torch.nn.functional.pad(x, flat)

kernel_name = 'interleave_layers__sliding_local_dilated__ssm_conv_s4d__prompt'

def setup_inputs():

    _w = (lambda a: (lambda t: t.to(torch.bfloat16) if t.is_floating_point() else t)(torch.as_tensor(a)))
    def _A_setup():
        B, S, D = 1, 2048, 640
        return {
            "x": _w((lambda *s: torch.randn(*s, dtype=torch.bfloat16) * 0.05)(B, S, D)),
            "wqkv": _w((lambda *s: torch.randn(*s, dtype=torch.bfloat16) * 0.05)(D, 3 * D)),
            "wo": _w((lambda *s: torch.randn(*s, dtype=torch.bfloat16) * 0.05)(D, D)),
        }
    _A_in = _A_setup()

    def _B_setup():
        Bsz, L, D, N = 1, 2048, 640, 192
        return {
            "u": _w((lambda *s: torch.randn(*s, dtype=torch.bfloat16) * 0.05)(Bsz, L, D)),
            "log_A_real": _w((lambda *s: torch.randn(*s, dtype=torch.bfloat16) * 3.2)(D, N) * 0.5),
            "A_imag": _w((lambda *s: torch.randn(*s, dtype=torch.bfloat16) * 0.1)(D, N) * 3.14),
            "C_real": _w((lambda *s: torch.randn(*s, dtype=torch.bfloat16) * 0.4)(D, N) / N ** 0.5),
            "C_imag": _w((lambda *s: torch.randn(*s, dtype=torch.bfloat16) * 0.4)(D, N) / N ** 0.5),
            "log_dt": _w((lambda *s: torch.randn(*s, dtype=torch.bfloat16) * 0.1)(D) * 0.5 - 4.0),
            "D_skip": _w((lambda *s: torch.randn(*s, dtype=torch.bfloat16) * 0.1)(D)),
        }
    _B_in = _B_setup()

    return {
        "A_x": _A_in["x"],
        "A_wqkv": _A_in["wqkv"],
        "A_wo": _A_in["wo"],
        "B_u": _B_in["u"],
        "B_log_A_real": _B_in["log_A_real"],
        "B_A_imag": _B_in["A_imag"],
        "B_C_real": _B_in["C_real"],
        "B_C_imag": _B_in["C_imag"],
        "B_log_dt": _B_in["log_dt"],
        "B_D_skip": _B_in["D_skip"],
    }

def reference(A_x, A_wqkv, A_wo, B_u, B_log_A_real, B_A_imag, B_C_real, B_C_imag, B_log_dt, B_D_skip):
    def _A_ref(x, wqkv, wo):
        B, S, D = x.shape
        H = 32; Dh = D // H
        W, dil = 8, 2
        qkv = (lambda x, *d: x.permute(*d))((x @ wqkv).reshape(B, S, 3, H, Dh), 2, 0, 3, 1, 4)
        q, k, v = qkv[0], qkv[1], qkv[2]
        scale = Dh ** -0.5
        pos = torch.arange(S)
        off = torch.arange(W) * dil
        idx = pos[:, None] - off[None, :]
        mask = idx >= 0
        idx_c = torch.where(mask, idx, 0).reshape(-1)
        kg = k[:, :, idx_c, :].reshape(B, H, S, W, Dh)
        vg = v[:, :, idx_c, :].reshape(B, H, S, W, Dh)
        logits = torch.einsum("bhsd,bhswd->bhsw", q, kg) * scale
        logits = torch.where(mask[None, None, :, :], logits, -1e9)
        attn = _softmax(logits, axis=-1)
        o = torch.einsum("bhsw,bhswd->bhsd", attn, vg)
        return (lambda x, *d: x.permute(*d))(o, 0, 2, 1, 3).reshape(B, S, D) @ wo

    def _B_ref(u, log_A_real, A_imag, C_real, C_imag, log_dt, D_skip):
        L = u.shape[1]
        dt = torch.exp(log_dt)
        A = -torch.exp(log_A_real) + 1j * A_imag
        C = (C_real + 1j * C_imag) * dt[:, None]
        pos = (lambda x, dt: x.to(dt))(torch.arange(L), log_dt.dtype)
        P = torch.exp((A * dt[:, None])[:, :, None] * pos[None, None, :])
        K = 2.0 * torch.einsum("dn,dnl->dl", C, P).real
        L2 = 2 * L
        u_t = (lambda x, *d: x.permute(*d))(u, 0, 2, 1)
        Kf = (lambda x, *a, **k: torch.fft.rfft(x.float(), *a, **k))(K, L2)
        Uf = (lambda x, *a, **k: torch.fft.rfft(x.float(), *a, **k))(u_t, L2)
        y = (lambda x, *a, **k: torch.fft.irfft(x, *a, **k).to(torch.bfloat16))(Uf * Kf[None, :, :], L2)[:, :, :L]
        y = (lambda x, *d: x.permute(*d))(y, 0, 2, 1)
        return y + u * D_skip[None, None, :]

    x = A_x
    x = x + _A_ref(_layernorm(x, axis=-1), A_wqkv, A_wo)
    x = x + _B_ref(_layernorm(x, axis=-1), B_log_A_real, B_A_imag, B_C_real, B_C_imag, B_log_dt, B_D_skip)
    x = x + _A_ref(_layernorm(x, axis=-1), A_wqkv, A_wo)
    x = x + _B_ref(_layernorm(x, axis=-1), B_log_A_real, B_A_imag, B_C_real, B_C_imag, B_log_dt, B_D_skip)
    return x
```

```cpp
#include <cuda_runtime.h>
#include <cuda.h>
#include <cuda_bf16.h>
#include <cuda_fp16.h>
#include <stdint.h>

typedef __nv_bfloat16 bf16;

constexpr int SEQ = 2048;
constexpr int DM  = 640;
constexpr int XP  = SEQ + 64;
constexpr int NMODE = 192;

__device__ __forceinline__ uint32_t s2u(const void* p) { return (uint32_t)__cvta_generic_to_shared(p); }
__device__ __forceinline__ void mbar_init(uint32_t b, int c) { asm volatile("mbarrier.init.shared::cta.b64 [%0], %1;" ::"r"(b), "r"(c)); }
__device__ __forceinline__ void mbar_expect(uint32_t b, uint32_t bytes) { asm volatile("mbarrier.arrive.expect_tx.shared::cta.b64 _, [%0], %1;" ::"r"(b), "r"(bytes) : "memory"); }
__device__ __forceinline__ void mbar_arrive(uint32_t b) { asm volatile("mbarrier.arrive.shared::cta.b64 _, [%0];" ::"r"(b) : "memory"); }
__device__ __forceinline__ void mbar_arrive_cta(uint32_t b, uint32_t cta) {
    asm volatile("{\n.reg .b32 ra;\nmapa.shared::cluster.u32 ra, %0, %1;\nmbarrier.arrive.shared::cluster.b64 _, [ra];\n}" ::"r"(b), "r"(cta) : "memory");
}
__device__ __forceinline__ void mbar_wait(uint32_t b, uint32_t ph) {
    asm volatile("{\n.reg .pred p;\nW: mbarrier.try_wait.parity.shared::cta.b64 p, [%0], %1;\n@p bra D;\nbra W;\nD:\n}" ::"r"(b), "r"(ph) : "memory");
}
__device__ __forceinline__ void fence_mbar_init() { asm volatile("fence.mbarrier_init.release.cluster;" ::: "memory"); }
__device__ __forceinline__ void cluster_sync() { asm volatile("barrier.cluster.arrive.aligned;\nbarrier.cluster.wait.aligned;" ::: "memory"); }
__device__ __forceinline__ void pdl_wait() { asm volatile("griddepcontrol.wait;" ::: "memory"); }
__device__ __forceinline__ void pdl_launch() { asm volatile("griddepcontrol.launch_dependents;" ::: "memory"); }
__device__ __forceinline__ void named_bar(int id, int n) { asm volatile("bar.sync %0, %1;" ::"r"(id), "r"(n) : "memory"); }
__device__ __forceinline__ void fence_async_smem() { asm volatile("fence.proxy.async.shared::cta;" ::: "memory"); }

__device__ __forceinline__ void tma2d(uint32_t dst, const CUtensorMap* m, int c0, int c1, uint32_t bar) {
    asm volatile("cp.async.bulk.tensor.2d.shared::cluster.global.mbarrier::complete_tx::bytes [%0], [%1, {%3, %4}], [%2];"
                 ::"r"(dst), "l"(m), "r"(bar), "r"(c0), "r"(c1) : "memory");
}
__device__ __forceinline__ void tma2d_mc(uint32_t dst, const CUtensorMap* m, int c0, int c1, uint32_t bar, uint16_t mask) {
    asm volatile("cp.async.bulk.tensor.2d.shared::cluster.global.mbarrier::complete_tx::bytes.multicast::cluster [%0], [%1, {%3, %4}], [%2], %5;"
                 ::"r"(dst), "l"(m), "r"(bar), "r"(c0), "r"(c1), "h"(mask) : "memory");
}
__device__ __forceinline__ void tma3d(uint32_t dst, const CUtensorMap* m, int c0, int c1, int c2, uint32_t bar) {
    asm volatile("cp.async.bulk.tensor.3d.shared::cluster.global.mbarrier::complete_tx::bytes [%0], [%1, {%3, %4, %5}], [%2];"
                 ::"r"(dst), "l"(m), "r"(bar), "r"(c0), "r"(c1), "r"(c2) : "memory");
}
__device__ __forceinline__ void tma3d_mc(uint32_t dst, const CUtensorMap* m, int c0, int c1, int c2, uint32_t bar, uint16_t mask) {
    asm volatile("cp.async.bulk.tensor.3d.shared::cluster.global.mbarrier::complete_tx::bytes.multicast::cluster [%0], [%1, {%3, %4, %5}], [%2], %6;"
                 ::"r"(dst), "l"(m), "r"(bar), "r"(c0), "r"(c1), "r"(c2), "h"(mask) : "memory");
}
__device__ __forceinline__ void bulk_g2s(uint32_t dst, const void* src, uint32_t bytes, uint32_t bar) {
    asm volatile("cp.async.bulk.shared::cluster.global.mbarrier::complete_tx::bytes [%0], [%1], %2, [%3];"
                 ::"r"(dst), "l"(src), "r"(bytes), "r"(bar) : "memory");
}
__device__ __forceinline__ void prefetch_tmap(const CUtensorMap* m) { asm volatile("prefetch.tensormap [%0];" ::"l"(m) : "memory"); }

__device__ __forceinline__ void wg_fence() { asm volatile("wgmma.fence.sync.aligned;" ::: "memory"); }
__device__ __forceinline__ void wg_commit() { asm volatile("wgmma.commit_group.sync.aligned;" ::: "memory"); }
template <int N> __device__ __forceinline__ void wg_wait() { asm volatile("wgmma.wait_group.sync.aligned %0;" ::"n"(N) : "memory"); }
__device__ __forceinline__ uint64_t mkdesc(uint32_t addr, uint32_t lbo, uint32_t sbo, uint32_t mode) {
    return (uint64_t)((addr & 0x3FFFF) >> 4) | ((uint64_t)(lbo >> 4) << 16) | ((uint64_t)(sbo >> 4) << 32) | ((uint64_t)mode << 62);
}

__device__ __forceinline__ void mma16816(float (&c)[4], uint32_t a0, uint32_t a1, uint32_t a2, uint32_t a3, uint32_t b0, uint32_t b1) {
    asm("mma.sync.aligned.m16n8k16.row.col.f32.bf16.bf16.f32 {%0,%1,%2,%3},{%4,%5,%6,%7},{%8,%9},{%0,%1,%2,%3};"
                 : "+f"(c[0]), "+f"(c[1]), "+f"(c[2]), "+f"(c[3]) : "r"(a0), "r"(a1), "r"(a2), "r"(a3), "r"(b0), "r"(b1));
}
__device__ __forceinline__ void mma1688(float (&c)[4], uint32_t a0, uint32_t a1, uint32_t b0) {
    asm("mma.sync.aligned.m16n8k8.row.col.f32.bf16.bf16.f32 {%0,%1,%2,%3},{%4,%5},{%6},{%0,%1,%2,%3};"
                 : "+f"(c[0]), "+f"(c[1]), "+f"(c[2]), "+f"(c[3]) : "r"(a0), "r"(a1), "r"(b0));
}
__device__ __forceinline__ void ldsm_x4(uint32_t& r0, uint32_t& r1, uint32_t& r2, uint32_t& r3, uint32_t a) {
    asm volatile("ldmatrix.sync.aligned.m8n8.x4.shared.b16 {%0,%1,%2,%3}, [%4];" : "=r"(r0), "=r"(r1), "=r"(r2), "=r"(r3) : "r"(a) : "memory");
}
__device__ __forceinline__ void ldsm_x4_t(uint32_t& r0, uint32_t& r1, uint32_t& r2, uint32_t& r3, uint32_t a) {
    asm volatile("ldmatrix.sync.aligned.m8n8.x4.trans.shared.b16 {%0,%1,%2,%3}, [%4];" : "=r"(r0), "=r"(r1), "=r"(r2), "=r"(r3) : "r"(a) : "memory");
}
__device__ __forceinline__ void ldsm_x2(uint32_t& r0, uint32_t& r1, uint32_t a) {
    asm volatile("ldmatrix.sync.aligned.m8n8.x2.shared.b16 {%0,%1}, [%2];" : "=r"(r0), "=r"(r1) : "r"(a) : "memory");
}
__device__ __forceinline__ void ldsm_x2_t(uint32_t& r0, uint32_t& r1, uint32_t a) {
    asm volatile("ldmatrix.sync.aligned.m8n8.x2.trans.shared.b16 {%0,%1}, [%2];" : "=r"(r0), "=r"(r1) : "r"(a) : "memory");
}
__device__ __forceinline__ void stsm_x4(uint32_t a, uint32_t r0, uint32_t r1, uint32_t r2, uint32_t r3) {
    asm volatile("stmatrix.sync.aligned.m8n8.x4.shared.b16 [%0], {%1,%2,%3,%4};" ::"r"(a), "r"(r0), "r"(r1), "r"(r2), "r"(r3) : "memory");
}
__device__ __forceinline__ void stsm_x2(uint32_t a, uint32_t r0, uint32_t r1) {
    asm volatile("stmatrix.sync.aligned.m8n8.x2.shared.b16 [%0], {%1,%2};" ::"r"(a), "r"(r0), "r"(r1) : "memory");
}
__device__ __forceinline__ uint32_t movm_t(uint32_t a) {
    uint32_t d;
    asm volatile("movmatrix.sync.aligned.m8n8.trans.b16 %0, %1;" : "=r"(d) : "r"(a));
    return d;
}
__device__ __forceinline__ uint32_t lds32(uint32_t a) { uint32_t v; asm volatile("ld.shared.u32 %0, [%1];" : "=r"(v) : "r"(a) : "memory"); return v; }
__device__ __forceinline__ uint32_t ldsv32(uint32_t a) { uint32_t v; asm volatile("ld.volatile.shared.u32 %0, [%1];" : "=r"(v) : "r"(a) : "memory"); return v; }
__device__ __forceinline__ void sts32(uint32_t a, uint32_t v) { asm volatile("st.shared.u32 [%0], %1;" ::"r"(a), "r"(v) : "memory"); }
__device__ __forceinline__ uint4 lds128(uint32_t a) { uint4 v; asm volatile("ld.shared.v4.u32 {%0,%1,%2,%3}, [%4];" : "=r"(v.x), "=r"(v.y), "=r"(v.z), "=r"(v.w) : "r"(a) : "memory"); return v; }
__device__ __forceinline__ void sts128(uint32_t a, uint4 v) { asm volatile("st.shared.v4.u32 [%0], {%1,%2,%3,%4};" ::"r"(a), "r"(v.x), "r"(v.y), "r"(v.z), "r"(v.w) : "memory"); }

__device__ __forceinline__ void stg128(void* p, uint4 v) { asm volatile("st.global.v4.u32 [%0], {%1,%2,%3,%4};" ::"l"(p), "r"(v.x), "r"(v.y), "r"(v.z), "r"(v.w) : "memory"); }

__device__ __forceinline__ uint4 ldg128(const void* p) { uint4 v; asm volatile("ld.global.v4.u32 {%0,%1,%2,%3}, [%4];" : "=r"(v.x), "=r"(v.y), "=r"(v.z), "=r"(v.w) : "l"(p) : "memory"); return v; }
__device__ __forceinline__ uint2 ldg64(const void* p) { uint2 v; asm volatile("ld.global.v2.u32 {%0,%1}, [%2];" : "=r"(v.x), "=r"(v.y) : "l"(p) : "memory"); return v; }
__device__ __forceinline__ uint32_t ldg32(const void* p) { uint32_t v; asm volatile("ld.global.u32 %0, [%1];" : "=r"(v) : "l"(p) : "memory"); return v; }

__device__ __forceinline__ uint32_t pack2(float lo, float hi) {
    uint32_t r;
    asm("cvt.rn.bf16x2.f32 %0, %1, %2;" : "=r"(r) : "f"(hi), "f"(lo));
    return r;
}
__device__ __forceinline__ float bf_lo(uint32_t v) { return __uint_as_float(v << 16); }
__device__ __forceinline__ float bf_hi(uint32_t v) { return __uint_as_float(v & 0xFFFF0000u); }
__device__ __forceinline__ float rbf(float x) { return __uint_as_float(pack2(0.f, x) & 0xFFFF0000u); }
__device__ __forceinline__ float ex2(float x) { float r; asm("ex2.approx.ftz.f32 %0, %1;" : "=f"(r) : "f"(x)); return r; }

__device__ __forceinline__ float2 ln_finish(float sum, float sumsq) {
    const float m = sum * (1.0f / DM);
    const float v = fmaxf(fmaf(sumsq, 1.0f / DM, -m * m), 0.f);
    float s, r;
    asm("sqrt.approx.ftz.f32 %0, %1;" : "=f"(s) : "f"(rbf(rbf(v) + 1e-5f)));
    asm("rcp.approx.ftz.f32 %0, %1;" : "=f"(r) : "f"(rbf(s)));
    return make_float2(m, r);
}
__device__ __forceinline__ uint32_t ln_finish_packed(float sum, float sumsq) {
    const float m = sum * (1.0f / DM);
    const float v = fmaxf(fmaf(sumsq, 1.0f / DM, -m * m), 0.f);
    float s;
    asm("sqrt.approx.ftz.f32 %0, %1;" : "=f"(s) : "f"(rbf(rbf(v) + 1e-5f)));
    return pack2(s, m);
}
__device__ __forceinline__ float frsq(float x) { float r; asm("rsqrt.approx.ftz.f32 %0, %1;" : "=f"(r) : "f"(x)); return r; }
__device__ __forceinline__ float frcp(float x) { float r; asm("rcp.approx.ftz.f32 %0, %1;" : "=f"(r) : "f"(x)); return r; }
__device__ __forceinline__ bool elect_one() {
    uint32_t p;
    asm volatile("{\n.reg .pred p;\nelect.sync _|p, 0xffffffff;\nselp.u32 %0, 1, 0, p;\n}" : "=r"(p));
    return p != 0;
}
__device__ __forceinline__ void cluster_arrive_relaxed() { asm volatile("barrier.cluster.arrive.relaxed.aligned;" ::: "memory"); }
__device__ __forceinline__ void cluster_wait() { asm volatile("barrier.cluster.wait.aligned;" ::: "memory"); }
template<int TA, int TB>
__device__ __forceinline__ void wgmma_n192(float (&d)[96], uint64_t da, uint64_t db, int scale_d) {
  asm volatile("{\n.reg .pred p;\nsetp.ne.b32 p, %98, 0;\n"
    "wgmma.mma_async.sync.aligned.m64n192k16.f32.bf16.bf16 "
    "{%0, %1, %2, %3, %4, %5, %6, %7, %8, %9, %10, %11, %12, %13, %14, %15, %16, %17, %18, %19, %20, %21, %22, %23, %24, %25, %26, %27, %28, %29, %30, %31, %32, %33, %34, %35, %36, %37, %38, %39, %40, %41, %42, %43, %44, %45, %46, %47, %48, %49, %50, %51, %52, %53, %54, %55, %56, %57, %58, %59, %60, %61, %62, %63, %64, %65, %66, %67, %68, %69, %70, %71, %72, %73, %74, %75, %76, %77, %78, %79, %80, %81, %82, %83, %84, %85, %86, %87, %88, %89, %90, %91, %92, %93, %94, %95}, %96, %97, p, 1, 1, %99, %100;\n}\n"
    : "+f"(d[0]), "+f"(d[1]), "+f"(d[2]), "+f"(d[3]), "+f"(d[4]), "+f"(d[5]), "+f"(d[6]), "+f"(d[7]), "+f"(d[8]), "+f"(d[9]), "+f"(d[10]), "+f"(d[11]), "+f"(d[12]), "+f"(d[13]), "+f"(d[14]), "+f"(d[15]), "+f"(d[16]), "+f"(d[17]), "+f"(d[18]), "+f"(d[19]), "+f"(d[20]), "+f"(d[21]), "+f"(d[22]), "+f"(d[23]), "+f"(d[24]), "+f"(d[25]), "+f"(d[26]), "+f"(d[27]), "+f"(d[28]), "+f"(d[29]), "+f"(d[30]), "+f"(d[31]), "+f"(d[32]), "+f"(d[33]), "+f"(d[34]), "+f"(d[35]), "+f"(d[36]), "+f"(d[37]), "+f"(d[38]), "+f"(d[39]), "+f"(d[40]), "+f"(d[41]), "+f"(d[42]), "+f"(d[43]), "+f"(d[44]), "+f"(d[45]), "+f"(d[46]), "+f"(d[47]), "+f"(d[48]), "+f"(d[49]), "+f"(d[50]), "+f"(d[51]), "+f"(d[52]), "+f"(d[53]), "+f"(d[54]), "+f"(d[55]), "+f"(d[56]), "+f"(d[57]), "+f"(d[58]), "+f"(d[59]), "+f"(d[60]), "+f"(d[61]), "+f"(d[62]), "+f"(d[63]), "+f"(d[64]), "+f"(d[65]), "+f"(d[66]), "+f"(d[67]), "+f"(d[68]), "+f"(d[69]), "+f"(d[70]), "+f"(d[71]), "+f"(d[72]), "+f"(d[73]), "+f"(d[74]), "+f"(d[75]), "+f"(d[76]), "+f"(d[77]), "+f"(d[78]), "+f"(d[79]), "+f"(d[80]), "+f"(d[81]), "+f"(d[82]), "+f"(d[83]), "+f"(d[84]), "+f"(d[85]), "+f"(d[86]), "+f"(d[87]), "+f"(d[88]), "+f"(d[89]), "+f"(d[90]), "+f"(d[91]), "+f"(d[92]), "+f"(d[93]), "+f"(d[94]), "+f"(d[95])
    : "l"(da), "l"(db), "r"(scale_d), "n"(TA), "n"(TB));
}

template<int TA, int TB>
__device__ __forceinline__ void wgmma_n48(float (&d)[24], uint64_t da, uint64_t db, int scale_d) {
  asm volatile("{\n.reg .pred p;\nsetp.ne.b32 p, %26, 0;\n"
    "wgmma.mma_async.sync.aligned.m64n48k16.f32.bf16.bf16 "
    "{%0, %1, %2, %3, %4, %5, %6, %7, %8, %9, %10, %11, %12, %13, %14, %15, %16, %17, %18, %19, %20, %21, %22, %23}, %24, %25, p, 1, 1, %27, %28;\n}\n"
    : "+f"(d[0]), "+f"(d[1]), "+f"(d[2]), "+f"(d[3]), "+f"(d[4]), "+f"(d[5]), "+f"(d[6]), "+f"(d[7]), "+f"(d[8]), "+f"(d[9]), "+f"(d[10]), "+f"(d[11]), "+f"(d[12]), "+f"(d[13]), "+f"(d[14]), "+f"(d[15]), "+f"(d[16]), "+f"(d[17]), "+f"(d[18]), "+f"(d[19]), "+f"(d[20]), "+f"(d[21]), "+f"(d[22]), "+f"(d[23])
    : "l"(da), "l"(db), "r"(scale_d), "n"(TA), "n"(TB));
}

template<int TA, int TB>
__device__ __forceinline__ void wgmma_n80(float (&d)[40], uint64_t da, uint64_t db, int scale_d) {
  asm volatile("{\n.reg .pred p;\nsetp.ne.b32 p, %42, 0;\n"
    "wgmma.mma_async.sync.aligned.m64n80k16.f32.bf16.bf16 "
    "{%0, %1, %2, %3, %4, %5, %6, %7, %8, %9, %10, %11, %12, %13, %14, %15, %16, %17, %18, %19, %20, %21, %22, %23, %24, %25, %26, %27, %28, %29, %30, %31, %32, %33, %34, %35, %36, %37, %38, %39}, %40, %41, p, 1, 1, %43, %44;\n}\n"
    : "+f"(d[0]), "+f"(d[1]), "+f"(d[2]), "+f"(d[3]), "+f"(d[4]), "+f"(d[5]), "+f"(d[6]), "+f"(d[7]), "+f"(d[8]), "+f"(d[9]), "+f"(d[10]), "+f"(d[11]), "+f"(d[12]), "+f"(d[13]), "+f"(d[14]), "+f"(d[15]), "+f"(d[16]), "+f"(d[17]), "+f"(d[18]), "+f"(d[19]), "+f"(d[20]), "+f"(d[21]), "+f"(d[22]), "+f"(d[23]), "+f"(d[24]), "+f"(d[25]), "+f"(d[26]), "+f"(d[27]), "+f"(d[28]), "+f"(d[29]), "+f"(d[30]), "+f"(d[31]), "+f"(d[32]), "+f"(d[33]), "+f"(d[34]), "+f"(d[35]), "+f"(d[36]), "+f"(d[37]), "+f"(d[38]), "+f"(d[39])
    : "l"(da), "l"(db), "r"(scale_d), "n"(TA), "n"(TB));
}

__device__ const __align__(1024) uint32_t c_fft[11264] = {
0x2ddc2dba,0x2fe62eb5,0x2ed02eb5,0xafffaf6e,0x2e1f2dfe,0x2e3f2fbc,0x2f022ee9,0xad27af30,0x2e5e2e3f,0x1fd92b5e,0x2f302f1a,0x244ea875,0x2e992e7c,0xad96a993,0x2f5a2f46,0x2e992c32,
0xad00ad72,0xa17eac32,0xa17ea515,0xabb79cb6,0xac07ac87,0x2dfe29f1,0x1fd99648,0xafedae99,0xa9f1ab05,0x2fd42fbc,0x26a1244e,0xad96af91,0xa765a8d5,0x2aaa2e3f,0x29932875,0x2515a8d5,
0xae99adfe,0xb000aee9,0xaf6eafbc,0x2c872f30,0xaf80af1a,0xac32af02,0xae7caf02,0xaaaa217e,0xaff4afc9,0x2b5e9cb6,0xad27addc,0xaff4ae7c,0xafedb000,0x2ffc2eb5,0xab05ac5d,0xacd8af5a,
0x2c072d27,0x9fd92bb7,0xadfead00,0x2fed2e1f,0x25db2993,0xaf6eacb0,0xaf6eaed0,0x2c5d2f46,0xa5151648,0xaddcafdd,0xafffafd4,0xac321648,0xabb7a934,0x28d5a814,0xafa0afed,0xaff4af30,
0x2f302e3f,0x2fed2f1a,0x28142b5e,0x2934a875,0x30002fc9,0x26a12ddc,0xa5db1cb6,0x30002e7c,0x2f462fd4,0xaed0aa4e,0xacb0aa4e,0x29932e99,0x2d272e5e,0xae3faffc,0xaf02adfe,0xae1fa814,
0xa9f1acd8,0x26a1ab05,0x2fd42ffc,0xad96afed,0x2515a30e,0x2fff2e1f,0x2ddc2f1a,0x2c32a30e,0x2d272aaa,0x28752e7c,0x28752c32,0x2fa02f80,0x2f912e99,0xaee9a9f1,0xa8141648,0x9fd92c87,
0xafa0ae7c,0xafafaf46,0x2d002993,0xafa0ac32,0xaf91b000,0x244eac5d,0x2fbc2eb5,0xab05af5a,0xac87ae5e,0x30002dfe,0x2f6e2ffc,0x2e992814,0x1cb6a875,0x25152e1f,0x2c322e1f,0x2d722ff4,
0x27652c87,0xa9932a4e,0xaaaaadba,0xa5152c87,0xabb7a44e,0xafa0af30,0x28d59fd9,0xaff4ae5e,0xaf91ae1f,0x2814abb7,0x2ee92d00,0x1fd9ad27,0xaf5aafff,0x2fd42ed0,0x2fd42fe6,0x30002ddc,
0x2f462f6e,0x2c322fdd,0x2e7c2fdd,0xa993b000,0xab5e2934,0xafafacd8,0xad00244e,0x2f1a2dfe,0xaee9afaf,0x2f30a17e,0xadfeaff8,0xafbca30e,0x2c5da765,0xa9f12ddc,0x2d969cb6,0x2c5dacb0,
0x2bb7a993,0x2f1aa515,0x2f1a2765,0xaff4aaaa,0x2e5e2fd4,0xab052dba,0x29342f6e,0x2ee9a6a1,0xadba1fd9,0xa5dbafed,0xafddac07,0xaa4e2dfe,0xacb0aff8,0x2ddc2f02,0x9cb6ae3f,0xa765aff8,
0xaeb5af91,0xaa4eafed,0x9648ae5e,0xac5d2d4d,0x2ddca17e,0x2e7c2e3f,0x2fc92e3f,0x1cb6afa0,0x2bb72fe6,0xaff8a993,0xab5e2aaa,0x2bb72fc9,0xafbcaa4e,0x2f30a5db,0xadfeafdd,0xaee9adba,
0xacd828d5,0xaf91230e,0xaf30af02,0x2c072fa0,0xac5dafff,0x2dbaac32,0x2dbaa515,0xae99addc,0x2fc929f1,0xa9932eb5,0x2aaa2fdd,0x2fe629f1,0xa30e2dfe,0xa17eafed,0xaff8ac07,0xafaf1fd9,
0x2dfe2faf,0x28142ff8,0xae5e217e,0x2ffc230e,0xaf5aa515,0xac87af46,0xa6a1af80,0xaf5a2765,0x1cb6ae99,0x2e7c2dba,0x2fc92dba,0x2ddcac5d,0x2f1a2ee9,0xafafab05,0xad002934,0xab5e2e5e,
0x2dbaa814,0x2fdd9fd9,0x25db2f91,0x2a4eaee9,0x27652faf,0xaf4628d5,0xaf80ae1f,0xa5152faf,0xafa0addc,0x2e3fac32,0x2e3fa515,0xa17eafff,0x2dfea6a1,0xacd82dba,0x244e2f6e,0x29342fd4,
0xad27afc9,0xa30eafff,0x2faf2d72,0xad27ae7c,0x2ffc2a4e,0x28142fdd,0xae5e25db,0x2dfe2dba,0xac5d2c07,0xaa4eaf91,0x9648af30,0xaeb5acd8,0xa993aff4,0x2c322f1a,0x2e7c2f1a,0x2f462bb7,
0xae7c26a1,0xafff1648,0x2d72aa4e,0xafc926a1,0x230eaee9,0x2ff89fd9,0x217e2f91,0x2fafa814,0x2d4d2fa0,0xafed230e,0xae5eaf02,0xaf9128d5,0xb000aaaa,0x2fdda515,0x2fdd2765,0x2f6ea993,
0x9cb63000,0xacb02fd4,0xa7652fd4,0x2ddcaf5a,0x217eaffc,0x2ff4ac07,0x2875afbc,0xaff82934,0xa44e2ff4,0xadfea8d5,0xa9342fa0,0x2cd82bb7,0x25dbafe6,0x16482f46,0x29f1af80,0x25dbafc9,
0x2ff41cb6,0x2e1f2765,0x2e1f2cb0,0xa875addc,0xafbca5db,0x1fd9af5a,0xad4dad96,0xacd82fdd,0x2f5a2934,0xaeb52ee9,0x2c5d2e5e,0x3000ab05,0xaed0ab5e,0x2f80a30e,0xaaaaaf02,0xacb0ab5e,
0x25dbaffc,0x2d96afbc,0x2f5aac07,0xafdd2934,0xaaaa2fa0,0xafc92875,0xafe62875,0x29932d27,0x2d00aed0,0x28d52d72,0x2ff89cb6,0x2d00afe6,0xae5e2d96,0x2d4dafd4,0xaf91a6a1,0xafed29f1,
0xafbca17e,0xad4da875,0x1fd9aff4,0xacd82ff8,0x2e992aaa,0xaa4e2fe6,0xaa4e2fc9,0x2fd4a993,0xacb0ad96,0x2fffac87,0x2d72aeb5,0xa765ad96,0x28752f30,0xab5eac07,0xaf1a2cd8,0xae3f2f91,
0xa9342ff4,0xae5e2fa0,0xaee9a8d5,0x2b052bb7,0x2d96aed0,0x2eb59cb6,0x2c872d72,0x2d96afe6,0xaf802c5d,0x2765af6e,0xa515af6e,0xaf4625db,0x2ff8a44e,0xaff42d4d,0xa8752ffc,0xa17e2ee9,
0x2f5a244e,0x2c5d2934,0xaeb52dfe,0x3000acd8,0xacb0ad00,0x2d72aff8,0x2fffa8d5,0xa765ad00,0x217e2f80,0xaf022515,0xaf02a765,0xaf1a2f46,0x2b05afdd,0xa8142f5a,0x2c072d96,0x2d4d25db,
0x2b5eafe6,0x2f02af80,0x230e2f46,0x2b5eafc9,0xaf302d96,0xacd8a6a1,0x2c07afd4,0xaf9129f1,0x2fdda44e,0xad962ffc,0xaf5a2d4d,0xa5db2ee9,0xad72abb7,0x2e7ca17e,0x2fc9a17e,0x2fffad00,
0xaed0a5db,0xaaaaa9f1,0x2f809648,0xacb0a5db,0x28752e5e,0xaf1a2f91,0xab5ead4d,0xae3f2fed,0x2b05aff8,0x2c072875,0xa8142ff4,0x2d4d217e,0xaf6e2d72,0x2eb5afc9,0x2eb5ae7c,0x2dbaafff,
0xaf802f5a,0xafc92e99,0xafe62e99,0x2f46ad96,0x28d52b05,0xaf022fed,0x230e2cd8,0x2fa0affc,0x2fbcaf02,0xa9342d27,0x2ffcae1f,0x2c07ae3f,0xa6a1ac32,0x2a4e9cb6,0x9648ad72,0xa6a1a515,
0x28752aaa,0xa8d52cb0,0xa8d52ed0,0x2e3faf80,0x2fedaeb5,0x29349648,0x2f30aa4e,0x2814ac5d,0x1648ad4d,0x2e99acd8,0x2c87afbc,0xa9f11fd9,0xafe62d27,0x2fffafaf,0xaddc230e,0xaed02d27,
0x2fd4af30,0x2f6eae5e,0x2dbaa44e,0xa6a19fd9,0x1cb6ad27,0x2fe6aff4,0x2ed0aff4,0xad722b5e,0xafaf2cb0,0x2e1faf46,0xa8d5a993,0xafaf2ed0,0xac072f6e,0x2934ac87,0xaffc2e99,0xafbc3000,
0xa44eab5e,0x2b05ad00,0x2f91afaf,0xafbc2f1a,0xafd42d72,0x1648a765,0x1648acb0,0xafdd2fff,0xac322f5a,0xaaaa26a1,0xaf802c87,0xae7c2f5a,0x2d009fd9,0xae1f2cd8,0xad272fbc,0xabb72d4d,
0xaffc2f02,0xaee92e1f,0x244ead27,0xad4d2e3f,0xa9f12e7c,0xafdd2f80,0xaeb52aaa,0xa9f12c32,0x2d72a5db,0xafe63000,0xaed03000,0x9cb626a1,0x2fa0afbc,0xaf022f91,0x230e2b05,0x28d5a44e,
0x96482c07,0xac872d4d,0xae992b05,0x29f1a814,0x2ed0abb7,0xa9932b5e,0xaf462ff8,0x2cb0abb7,0x2f1aafff,0xa30e2765,0xa30e2cb0,0x2e1fad72,0x1fd9ac5d,0x244e9648,0x2e5eaa4e,0x2f30aeb5,
0x2ff8aed0,0x2e3faddc,0xaf022fff,0x2ff8afe6,0x2d4daf6e,0x2ee9ae99,0xa44e2c87,0x2ffcb000,0xa6a1a814,0x2f6eaf30,0x2dbaa934,0x2fd4afed,0xaf462d00,0x2fc9afa0,0x2fe6afa0,0x2f80afaf,
0x2515ac5d,0x2d72ad96,0x1cb629f1,0x2c32ac5d,0xad002814,0x2d27ad4d,0x2e1fab05,0x2bb7ac07,0xaffc2f1a,0x2cd8ad00,0x2fedafaf,0x2b05ab5e,0xadba2f80,0x2c87acb0,0x2c87aed0,0x2a4eaaaa,
0x2f802f6e,0x2fc92fdd,0x2fe62fdd,0xaf46b000,0x2fa02f91,0x2bb72e5e,0x2ff42fed,0xa8d5ad4d,0x2fbc2faf,0xa934217e,0x2ffc2ff8,0x2c07230e,0x2fd42fc9,0xaf5aad72,0x30002fff,0x2fd42e7c,
0x2bb72aaa,0x2f1a2cb0,0x2f1a2ed0,0xaff4af80,0x2cd82c5d,0x2f303000,0x2f912f5a,0xac07aeb5,0x2dba2d4d,0x25db2cd8,0x2fdd2fbc,0x2a4e9fd9,0x2e7c2e1f,0xad72a875,0x2fff2ff4,0x2fc92e1f,
0xa6a1a934,0x29f1a44e,0x2d962cd8,0xafd4adfe,0x1cb6a17e,0x2fe62e3f,0x2ed02e3f,0xad72afa0,0x28752515,0x2d272f80,0x2fa02f46,0x2875a765,0x2c072a4e,0xa93425db,0x2ffc2fdd,0x2fbc2dba,
0xae5eaf1a,0xa934ae3f,0x2b052875,0xaee9ab5e,0xac5dad72,0x2dba2765,0x2dba2cb0,0xae99afff,0xa765aa4e,0x2f802fd4,0x2f462e99,0x2515aa4e,0x230e9fd9,0x217e2cd8,0x2ff82fbc,0x2faf2d4d,
0xaffcafaf,0xaee9aff8,0x244ea17e,0xad4da30e,0xaf6eafe6,0x25dbaaaa,0x2c5d2993,0xaf6eafc9,0xad72ae99,0x2fe62dba,0x2ed02dba,0x1cb6ac5d,0xa8d5ac07,0x2bb72f30,0x2ff42f91,0x2fa02cd8,
0xadbaac07,0xafddad4d,0xa5dbab05,0xaa4e2814,0xafc9af02,0xaaaaaf1a,0x2993217e,0xafe6af02,0xafa0afff,0x2e3f2765,0x2e3f2cb0,0xa17ead72,0xad4daeb5,0x2e5e3000,0x2fed2f5a,0x2f912c5d,
0xa17e2765,0xad001cb6,0xabb7addc,0xa17e2cb0,0xad4daa4e,0xaee9afdd,0x244ea5db,0xaffcadba,0xafd4aee9,0x29f1a934,0x2d962b05,0xa6a1ae5e,0xaf46aff4,0x2fc92f1a,0x2fe62f1a,0x2f802bb7,
0x2cb02eb5,0x1cb62dba,0xaddcaf6e,0x27652eb5,0xa30e2814,0xaff8ad4d,0xa17eab05,0xafafac07,0xadfeab5e,0xa44eae3f,0x2cd82875,0xa934af1a,0xb000af80,0x2fdd2cb0,0x2fdd2ed0,0x2f6e2aaa,
0x2d723000,0x25152fd4,0x2c322fd4,0x1cb6af5a,0xae1f9fd9,0xae3faee9,0xaf02a814,0x2d272f91,0xacd8aff4,0x2ffc28d5,0xab05afa0,0xafedabb7,0x2e992515,0xad962aaa,0x2f5a2993,0x2e99a765,
0x2ff42ddc,0x2e1f2ed0,0x2e1f2fe6,0xa875afff,0xa8142c87,0xaffca9f1,0xadfe1648,0x2e5e2e99,0xaf5aaf30,0x2eb5a814,0xac5dafed,0xb000a934,0x2c32a8d5,0xa9932e3f,0x2f462875,0x2e7ca8d5,
0x2e991fd9,0x30002814,0x2f6e2ee9,0xac87af91,0x29932fa0,0xaed02875,0xacb02875,0x2f462d27,0xaff4ac32,0x2b5eaddc,0xad27afff,0xaff4a515,0x244ead96,0x1fd92fd4,0x2f3026a1,0x2e5ea9f1,
0x2814ad27,0x2dfeabb7,0x2ffc2d00,0xae5eae1f,0x2e992f80,0xaa4e2e7c,0xaa4e2c32,0x2fd42aaa,0xae7c1648,0x9cb6afdd,0xaddcafd4,0xafc91648,0xa875af91,0x2b5e2fbc,0x2f1a244e,0x2e3fab05,
0xab05aff4,0x244eafa0,0x2fbc28d5,0xaf91abb7,0x30002c32,0x26a12fff,0xa5db2ddc,0x30002515,0xaaaa2c5d,0xac32af6e,0xae7caf6e,0xaf8025db,0xad27afed,0x2e3f2dfe,0x2f021fd9,0x2e1fac07,
0xaf5aae5e,0xac5daf30,0x2eb59fd9,0xb000a44e,0x2e7ca30e,0x2ddc2e1f,0x1cb62f1a,0x2fc9a30e,0x217e2f46,0xaf02acb0,0xaf02aed0,0xaf1a2993,0xaf30ae99,0x2fbc29f1,0x2ee99648,0x2dfeac87,
0xafa0a515,0xafafa993,0x2d00aaaa,0xafa02765,0x2934ad96,0x2fed26a1,0x28142fd4,0x2f30a9f1,0x2c872fed,0xb0009fd9,0xaf6eadfe,0xae992c07,0xafffabb7,0x2fe6a17e,0x2ed0a17e,0x2ddcad00,
0xac322c87,0xaf462a4e,0x2993adba,0xae7c2c87,0xa875afed,0x2f1aab05,0x2b5e2ffc,0x2e3facd8,0x2f302e1f,0xaee92bb7,0xafbcad00,0xadfe2d27,0xaf6e9cb6,0x2eb5ac32,0x2eb5a515,0x2dbaad72,
0xaaaa2f5a,0xaed02e99,0xacb02e99,0x2f80ad96,0x2b5eaf30,0x2fafa44e,0x2d00ae5e,0xaf1a9fd9,0xac072f02,0xab05ad27,0xad4d2e1f,0x28142e3f,0x2c5daed0,0xa9f12fff,0x2d96addc,0x2c5dafe6,
0x28752f80,0xa8d52fe6,0xa8d52fc9,0x2e3faf46,0xa44eafd4,0x2f91adba,0x2b05af6e,0xafbc26a1,0x96482ffc,0xae99a44e,0xac872ee9,0x29f12d4d,0x2515aff8,0x1cb62f02,0x2d72ae3f,0x2c32aff8,
0x2eb52b05,0x2a4e2cd8,0x16482fed,0x2c5daffc,0xad72ad27,0x2cb0aff4,0x2765aff4,0xafff2b5e,0x2bb72e7c,0xaff82aaa,0xab5e2f80,0x2bb72c32,0xa814af6e,0x2b052c87,0x2d4dae99,0x2c07b000,
0x2feda8d5,0x2f30a30e,0x29342f02,0x2814afa0,0xafd49cb6,0x1648aed0,0x1648afe6,0xafdd2d72,0x2ed029f1,0xaf462eb5,0xa9932fdd,0x2cb029f1,0xad00ad4d,0x2e1f244e,0x2d27aee9,0x2bb7affc,
0x2d4daf02,0x2fbcae1f,0x2cd82d27,0x9fd9ae3f,0xaf5a2cb0,0xac87a993,0xa6a1af46,0xaf5a2ed0,0x2fffa5db,0xacb03000,0xa7653000,0x2d7226a1,0xaf1aa814,0x2fafa934,0x2d00af30,0x2b5eafed,
0x1648afbc,0x2c87affc,0x2e992934,0xa9f1ac07,0xac322faf,0xaf8028d5,0xaaaaae1f,0xae7c2faf,0x2f1aad72,0xa30e2ed0,0xa30e2fe6,0x2e1f1cb6,0xaffc26a1,0x2fedadba,0x2cd8af6e,0x2b05afd4,
0xad27ac32,0xa30ead72,0x2faf9cb6,0xad27a515,0x1fd92f6e,0xafbc2e99,0xacd8ac87,0xad4d3000,0x2c5dafbc,0x2a4e2b05,0x16482f91,0x2eb5a44e,0xaf802d00,0x2ed0afa0,0x2cb0afa0,0x2aaaafaf,
0xafe626a1,0xaddc1648,0x2fffaa4e,0xaed026a1,0x2d002c07,0xad272ffc,0xae1fa934,0xabb72fbc,0x1fd9afa0,0x2e5ea30e,0x244e2f02,0x2f30a8d5,0xadba2f46,0x2c87afe6,0x2c87afc9,0x2a4eaf80,
0xafff2d96,0xae7c2c5d,0xafc92c5d,0x2d72a9f1,0xa17e2dfe,0xaff42fbc,0xa8752ee9,0x2ff8af30,0x2fedad00,0xad4d2f1a,0x2f91ab5e,0x2e5eafaf,0x25dbae7c,0x16482993,0x29f1af46,0x25dbac32,
0xae3f2fff,0xaff82fc9,0xaff82e7c,0x2f02ad72,0x2c0725db,0xadfe2f5a,0x9fd92d96,0x2fedafdd,0x2f6eaf91,0xa6a12c07,0x2fd4acd8,0x2dbaaf30,0xa765ab5e,0x2aaaa30e,0x2993af02,0x2515ab5e,
0xa5db2dfe,0xad962ee9,0xaf5a2fbc,0x2fddaf30,0x2f46ab5e,0xa7652bb7,0x25152bb7,0x2f80aff8,0x2d00afc9,0x28d59cb6,0x2ff8addc,0x2d00ae7c,0xacd89648,0x2dfeac5d,0x2934aeb5,0x244eaa4e,
0x2c07217e,0x9fd92875,0xadfe2ff4,0x2fedaff8,0x2fddaf46,0x29f1a515,0x29f12765,0x2eb5af80,0x2515ad96,0x2ddcac87,0x2fffaeb5,0x2c32ad96,0xaf022b05,0x2fa0aee9,0x28d5ae5e,0x230ea934,
0x2f91ad00,0x2cd8ab5e,0xac072f1a,0x2f30afaf,0x2d96afc9,0x2eb5addc,0x2c879cb6,0x2d96ae7c,0xa993a6a1,0x2fc9af5a,0x2fe6af5a,0x2aaaac87,0xaff82e5e,0x2ff4affc,0x2875adfe,0x217ea814,
0x2f6eafed,0x2fd4af91,0xa6a12d4d,0x2dbaae5e,0x2515ad00,0x2fffaff8,0x2ddca8d5,0x2c32ad00,0xae1f2993,0x2fafafe6,0x2fafafc9,0x28d5aaaa,0xaf912fdd,0x2ee9af5a,0x2814ad96,0x1fd9a5db,
0x2b5eae7c,0x2f02af46,0x230e2993,0x2b5eac32,0xab059648,0x2e5eaeb5,0x2ee9ac5d,0x2934aa4e,0xafdd2e5e,0x2d96adfe,0x2f5aaffc,0x25dba814,0xaddc2faf,0x2cb0ad27,0x2765ad27,0x1cb6a30e,
0xa765a5db,0x2993a9f1,0x2aaa9648,0x2515a5db,0xaf022cd8,0x28d5a934,0x2fa0adfe,0x230ea44e,0xaf912ff8,0x2814a875,0x2ee9aff4,0x1fd9a17e,0xaa4e2ddc,0x26a1a765,0x26a1acb0,0x16489cb6,
0x2d722d96,0x25152c5d,0x2c322c5d,0x1cb6a9f1,0x2d272d4d,0xad00a814,0x2bb72c07,0x2e1f2b05,0x2cd82d00,0xaffcaf1a,0x2b052b5e,0x2fed2faf,0x2c872cb0,0xadbaaf80,0x2a4e2aaa,0x2c872ed0,
0x2e3f2ddc,0x2ff82ed0,0x2ff82fe6,0xaf02afff,0x2ee92e99,0x2d4d2f6e,0x2ffc3000,0xa44eac87,0x2f6e2f30,0xa6a12814,0x2fd42fed,0x2dba2934,0x2fc92fa0,0xaf46ad00,0x2f802faf,0x2fe62fa0,
0xac87ad4d,0x9648ac07,0x29f12814,0xae99ab05,0xa993ab5e,0x2ed02bb7,0x2cb02bb7,0xaf46aff8,0xa30ea765,0x2f1a2fff,0x2e1f2d72,0xa30eacb0,0x244e1648,0x1fd92c5d,0x2f302eb5,0x2e5e2a4e,
0xaee9ae1f,0xaffcaf02,0xad4dae3f,0x244e2d27,0xafddaf80,0xa9f1ae7c,0xa9f1ac32,0xaeb5aaaa,0xafe6b000,0x2d7225db,0x9cb6a6a1,0xaed0b000,0xaf02af91,0x2fa02fbc,0x28d5244e,0x230eab05,
0x2b052d00,0xa44e2b5e,0xafbcaf1a,0x2f912faf,0x16482765,0xafd4ad72,0xafddafff,0x16482cb0,0xaaaaa6a1,0xac32af5a,0xae7caf5a,0xaf80ac87,0xae1facd8,0x2d001fd9,0xabb7ad4d,0xad27afbc,
0x2f6e2e5e,0x2fd42f30,0xa6a11fd9,0x2dba244e,0x2fe62ff4,0x1cb62d27,0xad72ab5e,0x2ed02ff4,0x2e1f2f46,0xafafacb0,0xafafaed0,0xa8d52993,0x29342c87,0xac07af6e,0xafbcb000,0xaffcae99,
0xa8d5acb0,0x2875aaaa,0x2e3f2f80,0xa8d5aed0,0x29341648,0x2fed2eb5,0x28142c5d,0x2f302a4e,0x2e992cd8,0x16482d4d,0xa9f19fd9,0x2c872fbc,0x2fff2faf,0xafe6ad27,0xaed0ad27,0xaddca30e,
0xafc9ae99,0xaf80af5a,0x2f462d96,0xafe6ae99,0xaf02afed,0x28d5ab05,0x2fa02ffc,0x230eacd8,0xa934ad27,0x2fbc2f02,0x2c072e3f,0x2ffc2e1f,0x2a4e1cb6,0xa6a12c32,0xa6a12515,0x96482d72,
0xaaaa29f1,0xaed025db,0xacb025db,0x2f801648,0xaf1aaf91,0x2875ae5e,0xae3fafed,0xab5e2d4d,0x2c07a875,0x2b052ff8,0x2d4da17e,0xa814aff4,0x2eb52fc9,0xaf6ead72,0x2dba2fff,0x2eb52e7c,
0x2f022f80,0x2b5e2fe6,0x2b5e2fc9,0x230eaf46,0xacd826a1,0xaf30ad96,0xaf91a9f1,0x2c072fd4,0xad96affc,0x2fdd244e,0xa5dbaee9,0xaf5aad4d,0x2e7c217e,0xad722bb7,0x2fff2d00,0x2fc9217e,
0x2c5da934,0x2f5aa44e,0x30002cd8,0xaeb5adfe,0x2d722ff8,0xacb02d00,0xa7652d00,0x2fff28d5,0xaf02a515,0x217eaf80,0xaf1aaf46,0xaf022765,0xa814af5a,0x2b052fdd,0x2d4da5db,0x2c07ad96,
0xae5eafa0,0xa934aff4,0x2b05abb7,0xaee928d5,0x2eb51cb6,0x2d962ed0,0x2d962fe6,0x2c87ad72,0x27652f6e,0xaf80ac5d,0xaf46a5db,0xa5152f6e,0xaff4ad4d,0x2ff8244e,0xa17eaee9,0xa875affc,
0xad4d2875,0xafbc217e,0xacd8aff8,0x1fd92ff4,0xaa4eafe6,0x2e99aaaa,0x2fd42993,0xaa4eafc9,0x2fff2c87,0xacb02d96,0xa7652d96,0x2d722eb5,0xab5e2c07,0x2875af30,0xae3faf91,0xaf1aacd8,
0x2d962fbc,0x25db2ffc,0xafdda934,0x2f5a2c07,0xafc9a875,0xaaaaafa0,0x2993ad27,0xafe6a875,0x28d5ad72,0x2d002ed0,0x2d002fe6,0x2ff81cb6,0x2d4d2fd4,0xae5ead96,0xafeda9f1,0xaf9126a1,
0x2e1fa765,0x2ff49cb6,0xa8752ddc,0x2e1facb0,0x1fd92f5a,0xafbc25db,0xacd8afdd,0xad4d2d96,0xaeb5aee9,0x2f5aa934,0x30002b05,0x2c5dae5e,0x2f80230e,0xaed02b5e,0xacb02b5e,0xaaaa2f02,
0xacb0afd4,0x9cb6b000,0x2ddc2f5a,0xa765afd4,0x2ff42c07,0x217e2ffc,0xaff8a934,0x28752fbc,0xadfe28d5,0xa44eaff4,0x2cd8abb7,0xa934afa0,0x1648af46,0x25db2fe6,0x25db2fc9,0x29f12f80,
0xafff9648,0xae7ca6a1,0xafc9a6a1,0x2d722a4e,0x2ff81fd9,0x230e2ee9,0x2faf2814,0x217eaf91,0xafeda30e,0x2d4dafa0,0xaf91a8d5,0xae5e2f02,0x2fdd2515,0xb0002aaa,0x2f6e2993,0x2fdda765,
0xa30e2fff,0xad272fc9,0xad272e7c,0x2fafad72,0x2814afdd,0x2ffcaa4e,0x2dfeadba,0xae5ea5db,0xaa4e2f91,0xac5dac07,0xaeb52cd8,0x96482f30,0x2c32af1a,0xa9932ff4,0x2f46abb7,0x2e7caf1a,
0x2fdd1fd9,0x2dba2814,0x2a4e2ee9,0x25dbaf91,0xaf46a8d5,0x2765afaf,0xa515afaf,0xaf802e1f,0x2e3f2c32,0xafa02ddc,0xa17e2fff,0x2e3f2515,0xacd8adba,0x2dfe26a1,0x2934afd4,0x244eaf6e,
0x2814aff8,0x2dfeafaf,0x2ffca30e,0xae5ea17e,0xac872f46,0xaf5a2515,0xaf5aa765,0xa6a12f80,0x2e7cadba,0x1cb62e99,0x2ddc2c5d,0x2fc9adba,0xafaf2b05,0x2f1aaee9,0xab5eae5e,0xad00a934,
0xaf91a30e,0xacd8a8d5,0x2c07afa0,0xaf302f02,0x2dba2c32,0xac5d2fff,0xae992ddc,0x2dba2515,0xa993aeb5,0x2fc9a9f1,0x2fe6a9f1,0x2aaaafdd,0xa17e2fed,0xa30eadfe,0xafaf9fd9,0xaff82c07,
0xaa4e2fed,0xaeb52f91,0xac5dad4d,0x96482e5e,0x2e7cae3f,0x2ddc217e,0x1cb62fa0,0x2fc9ae3f,0xaff82993,0x2bb7afe6,0x2bb7afc9,0xab5eaaaa,0x2f3025db,0xafbc2a4e,0xaee92dba,0xadfe2fdd,
0x2f1a2515,0x2bb72993,0xaff42aaa,0x2f1aa765,0xab05adba,0x2e5eafd4,0x2ee926a1,0x2934af6e,0xa5db2fed,0xadba9fd9,0xaa4eadfe,0xafdd2c07,0x2ddcaf02,0xacb02ff8,0xa7652ff8,0x9cb62e3f,
0x2c32afdd,0x2f46af6e,0xa9933000,0x2e7cafdd,0xafaf2cd8,0xab5ea934,0x2f1aadfe,0xad00a44e,0x2f30217e,0xaee92faf,0xafbc230e,0xadfe2ff8,0xa9f1addc,0x2c5d2765,0x2c5d2cb0,0x2d961cb6,
0xa993aa4e,0x2765ac87,0xa515ac87,0xaaaa2dba,0xafa02f30,0xabb7244e,0xaff42e5e,0x28d51fd9,0x28142bb7,0xaf912e1f,0x1fd92d27,0x2ee9ad00,0x2fd4aed0,0xaf5a2fff,0x3000addc,0x2fd4afe6,
0xafaf2f46,0xafa02e7c,0xafa02c32,0x2d00a993,0x244e2c5d,0xaf913000,0xab052f5a,0x2fbcaeb5,0x3000adfe,0xac872e5e,0x2e99a814,0x2f6eaffc,0x2515ae1f,0x1cb62875,0x2d72aff4,0x2c32ae1f,
0x26a12b05,0xa9f12cd8,0xad962fed,0x2fd4affc,0x2fffae1f,0x2515230e,0x2c32230e,0x2ddcaf1a,0x2875ae7c,0x2d27aaaa,0x2fa0af80,0x2875ac32,0xaee929f1,0x2f91ae99,0x9fd9ac87,0xa8149648,
0x2fedaf1a,0x2f30ae3f,0x29342875,0x2814ab5e,0x26a1addc,0x3000afc9,0x3000ae7c,0xa5db9cb6,0xaed02a4e,0x2f46afd4,0x2993ae99,0xacb02a4e,0xae3f2ffc,0x2d27ae5e,0xae1f2814,0xaf022dfe,
0x9fd9abb7,0x2c07ad27,0x2fedae1f,0xadfe2d00,0xaf6e2cb0,0x25dba993,0x2c5daf46,0xaf6e2ed0,0xaddc2fdd,0xa5159648,0xac329648,0xafff2fd4,0x28d52814,0xabb72934,0xaff42f30,0xafa02fed,
0xb0002ee9,0xae992dfe,0x2c87af30,0xaf6e2fbc,0xac322f02,0xaf802f1a,0xaaaaa17e,0xae7c2f02,0x2b5e1cb6,0xaff42fc9,0xaff42e7c,0xad272ddc,0x2ffcaeb5,0xafed3000,0xacd82f5a,0xab052c5d,
0xa17e2c32,0xad002d72,0xabb71cb6,0xa17e2515,0x2dfea9f1,0xac072c87,0xafed2e99,0x1fd91648,0x2fd4afbc,0xa9f12b05,0xad962f91,0x26a1a44e,0x2aaaae3f,0xa76528d5,0x251528d5,0x2993a875,
0x2fe6aeb5,0x2ddcadba,0xafff2f6e,0x2ed0aeb5,0x2e3fafbc,0x2e1fadfe,0xad272f30,0x2f02aee9,0x1fd9ab5e,0x2e5eae3f,0x244e2875,0x2f30af1a,0xad962993,0x2e99ae7c,0x2e99ac32,0x2f5aaf46,
0x299329f1,0xa76525db,0x251525db,0x2aaa1648,0x28d52934,0xaf02acd8,0x230e244e,0x2fa02dfe,0x28142875,0xaf91aff8,0x1fd9217e,0x2ee92ff4,0x26a12765,0xaa4eaddc,0x16481cb6,0x26a12cb0,
0x2f022f46,0x2b5e2e7c,0x2b5e2c32,0x230ea993,0x2e5e2eb5,0xab051648,0x29342a4e,0x2ee92c5d,0x2d962dfe,0xafddae5e,0x25db2814,0x2f5a2ffc,0x2cb02d27,0xaddcafaf,0x1cb6230e,0x27652d27,
0x2fd42f91,0x2f6e2fed,0x2dba2e5e,0xa6a1ad4d,0x2fff2ff8,0x25152d00,0x2c322d00,0x2ddc28d5,0x2faf2fe6,0xae1fa993,0x28d52aaa,0x2faf2fc9,0x2ee92f5a,0xaf91afdd,0x1fd925db,0x28142d96,
0x2cd82b5e,0x2f912d00,0x2f302faf,0xac07af1a,0x2eb52ddc,0x2d962fc9,0x2d962e7c,0x2c871cb6,0x2fc92f5a,0xa99326a1,0x2aaa2c87,0x2fe62f5a,0x2ff42ffc,0xaff8ae5e,0x217e2814,0x28752dfe,
0x9fd9a875,0x2c07a17e,0x2fed2ff8,0xadfeaff4,0x29f12515,0x2fdd2f46,0x2eb52f80,0x29f1a765,0x2ddc2c87,0x25152d96,0x2c322d96,0x2fff2eb5,0x2fa02ee9,0xaf02ab05,0x230e2934,0x28d52e5e,
0xad96aee9,0xa5dbadfe,0x2fdd2f30,0xaf5aafbc,0xa765abb7,0x2f462b5e,0x2f802ff8,0x2515abb7,0x28d51cb6,0x2d002fc9,0x2d002e7c,0x2ff82ddc,0x2dfe2c5d,0xacd81648,0x244e2a4e,0x29342eb5,
0xaff8afc9,0xae3fafff,0x2f022d72,0xaff8ae7c,0xadfeaf5a,0x2c07a5db,0x2fed2fdd,0x9fd9ad96,0xa6a1ac07,0x2f6e2f91,0x2dba2f30,0x2fd42cd8,0x2aaa230e,0xa7652b5e,0x25152b5e,0x29932f02,
0xae7cac5d,0xafffad96,0x2d7229f1,0xafc9ac5d,0xaff4afbc,0xa17eadfe,0x2ff82f30,0xa875aee9,0xad4daf1a,0x2fed2d00,0x2e5e2faf,0x2f912b5e,0x1648a993,0x25db2e7c,0x25db2c32,0x29f12f46,
0xaddc9648,0xafe6a6a1,0xaed0a6a1,0x2fff2a4e,0xad27affc,0x2d00ac07,0xabb7afbc,0xae1f2934,0x2e5e230e,0x1fd92fa0,0x2f3028d5,0x244eaf02,0x2c872fe6,0xadbaaf46,0x2a4e2f80,0x2c872fc9,
0xa30e2d72,0xad272c32,0xad272515,0x2faf1cb6,0xafbcae99,0x1fd9af6e,0xad4db000,0xacd82c87,0x2a4eab05,0x2c5d2fbc,0x2eb5244e,0x1648af91,0x2ed02fa0,0xaf80ad00,0x2aaa2faf,0x2cb02fa0,
0x2c872ffc,0x16482fbc,0xa9f12c07,0x2e99a934,0xaf80a8d5,0xac32afaf,0xae7cafaf,0xaaaa2e1f,0xa30eaed0,0x2f1a2d72,0x2e1f9cb6,0xa30eafe6,0x2fed2dba,0xaffca6a1,0x2b052fd4,0x2cd82f6e,
0x2fbc2e1f,0x2d4d2f02,0x9fd92e3f,0x2cd8ad27,0xac872993,0xaf5aacb0,0xaf5aaed0,0xa6a12f46,0xacb0b000,0x2fff25db,0x2d72a6a1,0xa765b000,0x2faf2934,0xaf1a2814,0x2b5e2fed,0x2d002f30,
0x2f30230e,0x2fed28d5,0x28142fa0,0x2934af02,0x16482ed0,0xafd41cb6,0xafddad72,0x16482fe6,0xaf46aeb5,0x2ed0a9f1,0x2cb0a9f1,0xa993afdd,0x2e1fa44e,0xad002d4d,0x2bb72ffc,0x2d272ee9,
0x2a4eacd8,0x2eb5ab05,0x2c5d2ffc,0x1648afed,0x2cb02ff4,0xad722d27,0xafffab5e,0x27652ff4,0xaff8aaaa,0x2bb7ae7c,0x2bb7ac32,0xab5eaf80,0x2b05ac87,0xa8142f6e,0x2c073000,0x2d4d2e99,
0xa8d5afe6,0x2875af80,0x2e3f2f46,0xa8d5afc9,0x2f912dba,0xa44e2fd4,0xafbca6a1,0x2b052f6e,0xae99244e,0x9648affc,0x29f1ad4d,0xac87aee9,0x1cb6af02,0x25152ff8,0x2c322ff8,0x2d722e3f,
0xaed0ae99,0xaaaaaf5a,0x2f802d96,0xacb0ae99,0x2faf244e,0x2b5e2f30,0xaf1a1fd9,0x2d002e5e,0xab052d27,0xac07af02,0x2814ae3f,0xad4dae1f,0xa9f1afff,0x2c5d2ed0,0x2c5d2fe6,0x2d962ddc,
0xaf46aa4e,0xac32ac87,0xae7cac87,0x29932dba,0x2f1a2b05,0xa8752fed,0x2e3f2cd8,0x2b5eaffc,0xaee9abb7,0x2f30ae1f,0xadfead27,0xafbc2d00,0x2eb52c32,0xaf6e1cb6,0x2dba2d72,0x2eb52515,
0xafaf2993,0xafa02515,0xafa0a765,0x2d002aaa,0x2feda6a1,0x29342d96,0x2f3029f1,0x2814afd4,0xb0001fd9,0x2c87afed,0xae99ac07,0xaf6e2dfe,0x2fe6217e,0xafff2bb7,0x2ddc2d00,0x2ed0217e,
0xac5d2f30,0xaf5a2e5e,0xb000244e,0x2eb51fd9,0x2ddcae1f,0x2e7c230e,0x2fc9230e,0x1cb6af1a,0xaf022cb0,0x217eaf46,0xaf1aa993,0xaf022ed0,0x2fbca9f1,0xaf302e99,0x2dfe2c87,0x2ee91648,
0x244e2fa0,0xab052ff4,0xaf912bb7,0x2fbca8d5,0x26a1afff,0x3000ac32,0x3000a515,0xa5dbaddc,0xac322f6e,0xaaaaac5d,0xaf80a5db,0xae7c2f6e,0x2e3fadfe,0xad272fed,0x2e1f2c07,0x2f029fd9,
0x2dfe2bb7,0x28142d27,0xae5e2e1f,0x2ffcad00,0xaa4eae7c,0x2e99af80,0x2fd4aaaa,0xaa4eac32,0x9cb62fdd,0xae7c9648,0xafc99648,0xaddc2fd4,0x2b5eafbc,0xa8752f91,0x2e3f2b05,0x2f1aa44e,
0x3000a814,0x2e999fd9,0xac872f91,0x2f6eaee9,0xaed0a875,0x2993afa0,0x2f46ad27,0xacb0a875,0x2b5e2ddc,0xaff42c32,0xaff42515,0xad272fff,0x1fd9afd4,0x244e2d96,0x2e5e29f1,0x2f30a6a1,
0x2e1faed0,0x2ff4addc,0xa8752fff,0x2e1fafe6,0xaffc29f1,0xa814ac87,0x2e5eae99,0xadfe9648,0x2eb52814,0xaf5a2f30,0xb0002934,0xac5d2fed,0xa993ae3f,0x2c3228d5,0x2e7c28d5,0x2f46a875,
0x2515afd4,0x2d72b000,0x1cb62f5a,0x2c32afd4,0xae3f2ee9,0xae1f1fd9,0x2d27af91,0xaf022814,0x2ffca8d5,0xacd82ff4,0xafed2bb7,0xab052fa0,0xad96aaaa,0x2e99a515,0x2e992765,0x2f5aa993,
0x1cb6adba,0x2cb0aeb5,0x2765aeb5,0xaddc2f6e,0xaff82d4d,0xa30ea814,0xafaf2c07,0xa17e2b05,0xa44e2e3f,0xadfe2b5e,0xa9342f1a,0x2cd8a875,0x2fddacb0,0xb0002f80,0x2f6eaaaa,0x2fddaed0,
0xad009cb6,0xa17ea765,0xa17eacb0,0xabb72ddc,0xaee92fdd,0xad4d2a4e,0xaffc2dba,0x244e25db,0x29f12934,0xafd42ee9,0xa6a12e5e,0x2d96ab05,0x2fc9af1a,0xaf462ff4,0x2f80abb7,0x2fe6af1a,
0xafdd2d4d,0xadba2c07,0xaa4ea814,0xa5db2b05,0xaaaa2f1a,0xafc92f02,0xafe62f02,0x2993a17e,0x2e3fa765,0xafa02fff,0xa17e2d72,0x2e3facb0,0x2e5eb000,0xad4d2eb5,0x2f91ac5d,0x2fedaf5a,
0xaee92ff8,0xaffc2faf,0xad4d230e,0x244e217e,0x25db2aaa,0xaf6e2fe6,0xaf6e2fc9,0x2c5da993,0x2fe6adba,0xad722e99,0x1cb62c5d,0x2ed0adba,0x2bb7af30,0xa8d52c07,0x2fa0acd8,0x2ff4af91,
0xa9342e3f,0xae5e2f1a,0xaee92b5e,0x2b05a875,0x2dbaa765,0xac5d2d72,0xae992fff,0x2dbaacb0,0x2f80afd4,0xa7652a4e,0x25152a4e,0x2f46ae99,0x217eacd8,0x230e1fd9,0x2fafad4d,0x2ff8afbc,
0x29f1244e,0xa6a12934,0xafd42dfe,0x2d96acd8,0x2fe6ae3f,0x1cb6217e,0xad722fa0,0x2ed0ae3f,0x2d27af80,0x2875a515,0x28752765,0x2fa0af46,0xa934a5db,0x2c07aa4e,0x2fbcadba,0x2ffcafdd,
0x2f1aacb0,0x2bb7aaaa,0xaff42f80,0x2f1aaed0,0x2f30b000,0x2cd8ac5d,0xac072eb5,0x2f91af5a,0x25dbacd8,0x2dbaad4d,0x2a4e1fd9,0x2fddafbc,0xad722875,0x2e7cae1f,0x2fc9ae1f,0x2fffaff4,
0x2fc9afdd,0x2f80af6e,0xaf463000,0x2fe6afdd,0x2bb7ae5e,0x2fa0af91,0xa8d52d4d,0x2ff4afed,0xa934a17e,0x2fbcafaf,0x2c07a30e,0x2ffcaff8,0xaf5a2d72,0x2fd4afc9,0x2fd4ae7c,0x3000afff,
0x3c003c00,0x3bff3c00,0x3c003c00,0x3bfa3bfd,0x3c003c00,0x3bef3bf5,0x3c003c00,0x3bde3be7,0x3c003c00,0x3bc83bd4,0x3c003c00,0x3bac3bbb,0x3c003c00,0x3b8b3b9d,0x3bff3c00,0x3b653b79,
0x3c003c00,0x3bff3c00,0x3c003c00,0x3bf83bfd,0x3bff3c00,0x3bea3bf2,0x3bff3bff,0x3bd63be1,0x3bfe3bff,0x3bba3bc9,0x3bfd3bfe,0x3b983baa,0x3bfc3bfd,0x3b6f3b84,0x3bfb3bfc,0x3b3f3b58,
0x3c003c00,0x3bff3c00,0x3bff3c00,0x3bf63bfc,0x3bfe3bff,0x3be53bef,0x3bfd3bfe,0x3bcc3bda,0x3bfb3bfc,0x3bab3bbc,0x3bf93bfa,0x3b813b97,0x3bf63bf7,0x3b4f3b69,0x3bf23bf4,0x3b163b33,
0x3c003c00,0x3bff3c00,0x3bff3c00,0x3bf53bfb,0x3bfd3bfe,0x3be03bec,0x3bfa3bfc,0x3bc23bd2,0x3bf63bf8,0x3b9a3baf,0x3bf23bf4,0x3b683b82,0x3bec3bef,0x3b2c3b4b,0x3be53be9,0x3ae83b0b,
0x3c003c00,0x3bfe3c00,0x3bfe3bff,0x3bf23bfa,0x3bfb3bfd,0x3bda3be8,0x3bf63bf9,0x3bb73bca,0x3bf03bf4,0x3b873ba0,0x3be83bed,0x3b4c3b6b,0x3bdf3be4,0x3b073b2b,0x3bd43bda,0x3ab63ae0,
0x3c003c00,0x3bfe3c00,0x3bfd3bff,0x3bf03bf9,0x3bf93bfb,0x3bd43be4,0x3bf23bf6,0x3bab3bc1,0x3be83bed,0x3b733b91,0x3bdd3be3,0x3b2f3b53,0x3bcf3bd6,0x3ade3b08,0x3bbf3bc7,0x3a813ab1,
0x3c003c00,0x3bfe3c00,0x3bfc3bfe,0x3bee3bf8,0x3bf63bf9,0x3bce3be0,0x3bec3bf1,0x3b9e3bb7,0x3bdf3be6,0x3b5e3b80,0x3bcf3bd7,0x3b103b39,0x3bbc3bc6,0x3ab33ae3,0x3ba53bb1,0x3a493a7f,
0x3bff3c00,0x3bfe3c00,0x3bfb3bfe,0x3beb3bf7,0x3bf23bf7,0x3bc63bdb,0x3be53bed,0x3b903bad,0x3bd43bdd,0x3b473b6e,0x3bbf3bca,0x3aee3b1d,0x3ba53bb2,0x3a853abc,0x3b873b97,0x3a0d3a4b,
0x3bfd3c00,0x3bfa3c00,0x3be83bf6,0x3bcc3be9,0x3bbf3bd6,0x3b713ba4,0x3b813ba2,0x3aeb3b33,0x3b2f3b5a,0x3a3d3a99,0x3acb3aff,0x396b39d8,0x3a543a92,0x387a38f6,0x39cd3a13,0x36dd37ee,
0x3bfd3c00,0x3bfa3c00,0x3be53bf4,0x3bc83be7,0x3bb73bd1,0x3b653b9d,0x3b713b97,0x3ad53b22,0x3b163b46,0x3a193a7c,0x3aa53ae0,0x393739ad,0x3a213a65,0x383538ba,0x398b39d8,0x36313753,
0x3bfd3c00,0x3bf93c00,0x3be23bf3,0x3bc33be5,0x3bae3bcb,0x3b593b95,0x3b603b8a,0x3abd3b11,0x3afb3b30,0x39f43a5e,0x3a7e3abf,0x39023980,0x39eb3a37,0x37dd387c,0x3946399b,0x358136b5,
0x3bfc3c00,0x3bf93c00,0x3bdf3bf1,0x3bbf3be3,0x3ba53bc6,0x3b4c3b8c,0x3b4f3b7d,0x3aa53aff,0x3ade3b1a,0x39cd3a3f,0x3a543a9c,0x38cc3951,0x39b33a07,0x374e383d,0x38fd395b,0x34cf3614,
0x3bfc3c00,0x3bf83c00,0x3bdc3bf0,0x3bba3be1,0x3b9c3bc0,0x3b3f3b84,0x3b3d3b70,0x3a8c3aed,0x3ac13b02,0x39a63a1f,0x3a293a78,0x38943922,0x397939d4,0x36bb37f9,0x38b23918,0x341a3570,
0x3bfc3c00,0x3bf83c00,0x3bd83bee,0x3bb53bdf,0x3b923bb9,0x3b323b7b,0x3b2a3b62,0x3a733ad9,0x3aa23ae9,0x397d39fe,0x39fc3a52,0x385a38f1,0x393c399f,0x36253775,0x386538d3,0x32c634c9,
0x3bfb3c00,0x3bf73c00,0x3bd43bed,0x3bb03bdc,0x3b873bb2,0x3b243b72,0x3b163b53,0x3a583ac6,0x3a813ad0,0x395439dc,0x39cd3a2b,0x382038bf,0x38fd3969,0x358d36ee,0x3815388c,0x31533420,
0x3bfb3c00,0x3bf63c00,0x3bd03beb,0x3bab3bda,0x3b7c3bab,0x3b163b69,0x3b013b43,0x3a3d3ab1,0x3a603ab5,0x392939ba,0x399d3a02,0x37c8388c,0x38bc3930,0x34f33665,0x37853842,0x2fbd32ea,
0x3bf63c00,0x3bf03c00,0x3ba53bd7,0x3b733bc1,0x3b073b5f,0x3a813b08,0x3a213a9c,0x392939e1,0x38fd3996,0x36ff385d,0x374e3858,0x327c3529,0x345735da,0xa9b12d1a,0x2cce3191,0xb49fb160,
0x3bf53c00,0x3bef3c00,0x3b9f3bd5,0x3b6c3bbe,0x3af73b55,0x3a6f3afc,0x3a043a87,0x390739c7,0x38d13972,0x36993832,0x36d23822,0x316c34b1,0x3371354c,0xad65297f,0x27763036,0xb552b2b9,
0x3bf53c00,0x3bef3c00,0x3b9a3bd2,0x3b653bbb,0x3ae83b4b,0x3a5c3af0,0x39e73a71,0x38e539ad,0x38a3394d,0x36313807,0x365437d8,0x305b3438,0x323234bd,0xafef1e48,0xa4522db0,0xb602b408,
0x3bf43c00,0x3bee3c00,0x3b943bd0,0x3b5e3bb7,0x3ad83b41,0x3a493ae3,0x39c93a5a,0x38c13992,0x38743927,0x35c837b7,0x35d4376a,0x2e91337d,0x30f0342c,0xb13ba7da,0xac0629e3,0xb6afb4b1,
0x3bf33c00,0x3bed3c00,0x3b8e3bcd,0x3b573bb4,0x3ac73b36,0x3a353ad6,0x39aa3a43,0x389e3976,0x38453900,0x355e375e,0x355236f9,0x2c6a3288,0x2f593334,0xb27cac51,0xaef51a48,0xb759b558,
0x3bf23c00,0x3bec3c00,0x3b873bca,0x3b4f3bb1,0x3ab63b2b,0x3a213ac9,0x398b3a2b,0x387a395b,0x381538d8,0x34f33705,0x34cf3687,0x28843191,0x2cce320d,0xb3baaeaa,0xb0f0a91b,0xb7feb5fd,
0x3bf23c00,0x3beb3c00,0x3b813bc7,0x3b473bad,0x3aa53b20,0x3a0d3abc,0x396b3a13,0x3855393e,0x37c838b0,0x348736aa,0x344b3614,0x16483099,0x288430e4,0xb47bb080,0xb263ad4c,0xb850b69e,
0x3bf13c00,0x3bea3c00,0x3b7a3bc4,0x3b3f3baa,0x3a933b14,0x39f83aae,0x394a39fa,0x38303922,0x37643887,0x341a364e,0x3389359f,0xa81f2f40,0x9cb62f72,0xb517b1aa,0xb3d3b004,0xb89eb73d,
0x3be93c00,0x3be13c00,0x3b373ba6,0x3af13b86,0x39e33aa0,0x392e3a27,0x380a3905,0x3599380d,0x335935f1,0x217f31db,0xac382d4c,0xb546b12e,0xb5b1b2d2,0xb90cb7cd,0xb8eab7d8,0xbadbba0b,
0x3be83c00,0x3be03c00,0x3b2f3ba2,0x3ae83b82,0x39cd3a92,0x39163a17,0x37c838e7,0x354637d8,0x327c3593,0xa4523115,0xae5f2aac,0xb5c8b226,0xb648b3f7,0xb94ab828,0xb933b838,0xbb0aba43,
0x3be73c00,0x3bdf3c00,0x3b273b9e,0x3ade3b7d,0x39b83a83,0x38fd3a07,0x377a38c9,0x34f33796,0x319e3534,0xa9b1304e,0xb042257f,0xb648b31b,0xb6ddb48d,0xb986b867,0xb979b881,0xbb35ba78,
0x3be63c00,0x3bde3c00,0x3b1e3b9b,0x3ad53b79,0x39a13a74,0x38e539f6,0x372c38ab,0x349f3753,0x30be34d5,0xac9c2f0e,0xb153a0b6,0xb6c6b408,0xb76fb51d,0xb9c0b8a6,0xb9bcb8c9,0xbb5cbaaa,
0x3be53c00,0x3bdd3c00,0x3b163b97,0x3acb3b74,0x398b3a65,0x38cc39e5,0x36dd388c,0x344b3710,0x2fbd3475,0xae5f2d7e,0xb263a91b,0xb742b481,0xb7feb5ab,0xb9f8b8e2,0xb9fcb90e,0xbb7fbad9,
0x3be43c00,0x3bdc3c00,0x3b0d3b93,0x3ac13b70,0x39743a56,0x38b239d4,0x368d386d,0x33eb36cc,0x2dfb3414,0xb0102bd9,0xb371ac83,0xb7bdb4f9,0xb845b637,0xba2db91d,0xba39b951,0xbb9ebb05,
0x3be33c00,0x3bda3c00,0x3b043b8f,0x3ab63b6b,0x395d3a47,0x389939c3,0x363c384d,0x33403687,0x2c383365,0xb0f028b6,0xb43eae78,0xb81ab570,0xb889b6c1,0xba60b956,0xba73b992,0xbbb8bb2e,
0x3be23c00,0x3bd93c00,0x3afb3b8a,0x3aac3b67,0x39463a37,0x387f39b1,0x35eb382d,0x32943642,0x28e832a1,0xb1cf2248,0xb4c3b036,0xb855b5e5,0xb8ccb748,0xba90b98d,0xbaa9b9d0,0xbbcfbb53,
0x3c003c00,0x3bfe3c00,0x3c003c00,0x3bf73bfc,0x3c003c00,0x3beb3bf2,0x3c003c00,0x3bd93be3,0x3c003c00,0x3bc13bce,0x3c003c00,0x3ba53bb4,0x3c003c00,0x3b823b94,0x3bff3bff,0x3b5b3b6f,
0x3c003c00,0x3bfe3c00,0x3c003c00,0x3bf53bfb,0x3bff3c00,0x3be63bee,0x3bff3bff,0x3bcf3bdb,0x3bfe3bfe,0x3bb23bc1,0x3bfd3bfe,0x3b8e3ba1,0x3bfc3bfd,0x3b643b7a,0x3bfb3bfb,0x3b333b4c,
0x3c003c00,0x3bfe3c00,0x3bff3c00,0x3bf33bf9,0x3bfe3bff,0x3be03beb,0x3bfd3bfd,0x3bc53bd3,0x3bfb3bfc,0x3ba13bb4,0x3bf83bf9,0x3b753b8c,0x3bf53bf7,0x3b413b5c,0x3bf23bf3,0x3b063b25,
0x3c003c00,0x3bfd3c00,0x3bff3bff,0x3bf03bf8,0x3bfc3bfe,0x3bda3be6,0x3bf93bfb,0x3bb93bca,0x3bf53bf7,0x3b8e3ba5,0x3bf03bf3,0x3b5a3b75,0x3beb3bee,0x3b1c3b3c,0x3be43be7,0x3ad53afa,
0x3c003c00,0x3bfd3c00,0x3bfe3bff,0x3bee3bf7,0x3bfa3bfc,0x3bd33be2,0x3bf53bf8,0x3bac3bc1,0x3bee3bf2,0x3b7a3b94,0x3be63beb,0x3b3c3b5c,0x3bdd3be2,0x3af43b19,0x3bd13bd7,0x3aa13acb,
0x3bff3c00,0x3bfc3c00,0x3bfc3bfe,0x3beb3bf5,0x3bf73bfa,0x3bcb3bdd,0x3bf03bf4,0x3b9e3bb6,0x3be63beb,0x3b643b82,0x3bda3be0,0x3b1c3b41,0x3bcb3bd3,0x3ac83af4,0x3bba3bc3,0x3a683a9a,
0x3bff3c00,0x3bfb3bff,0x3bfb3bfd,0x3be73bf3,0x3bf43bf8,0x3bc33bd7,0x3be93bef,0x3b8f3bab,0x3bdb3be3,0x3b4c3b6f,0x3bca3bd3,0x3afa3b25,0x3bb63bc1,0x3a9a3acb,0x3b9f3bab,0x3a2c3a65,
0x3bff3c00,0x3bfb3bff,0x3bf93bfd,0x3be43bf2,0x3bf03bf5,0x3bba3bd1,0x3be23be9,0x3b7f3b9f,0x3bcf3bd9,0x3b333b5b,0x3bb93bc5,0x3ad53b06,0x3b9e3bac,0x3a683aa1,0x3b7f3b8f,0x39ec3a2c,
0x3bfa3bff,0x3bf33bff,0x3be03bf0,0x3bba3bdc,0x3bb13bcb,0x3b533b8c,0x3b6e3b92,0x3ac33b10,0x3b183b45,0x3a0c3a6c,0x3aaf3ae5,0x393139a3,0x3a343a73,0x383938b9,0x39a939f1,0x36513767,
0x3bf93bff,0x3bf23bfe,0x3bdc3bee,0x3bb43bd9,0x3ba73bc5,0x3b453b82,0x3b5c3b85,0x3aa93afd,0x3afb3b2e,0x39e43a4c,0x3a863ac3,0x38fa3973,0x39fd3a44,0x37e03878,0x396339b2,0x359c36c3,
0x3bf93bff,0x3bf13bfe,0x3bd83beb,0x3bae3bd6,0x3b9d3bbe,0x3b373b78,0x3b493b76,0x3a8f3ae9,0x3add3b16,0x39bb3a2a,0x3a5b3a9f,0x38c03942,0x39c43a12,0x374b3836,0x39193971,0x34e4361d,
0x3bf83bff,0x3bf03bfe,0x3bd33be9,0x3ba73bd3,0x3b923bb6,0x3b273b6e,0x3b353b67,0x3a733ad4,0x3abe3afd,0x39913a08,0x3a2e3a79,0x38853910,0x398839de,0x36b237e6,0x38cd392d,0x34293573,
0x3bf73bff,0x3bee3bfe,0x3bcf3be7,0x3ba13bcf,0x3b873baf,0x3b183b64,0x3b203b57,0x3a573abe,0x3a9d3ae2,0x396539e4,0x39ff3a51,0x384938dc,0x394939a7,0x3617375c,0x387e38e6,0x32d834c6,
0x3bf63bff,0x3bed3bfe,0x3bca3be4,0x3b9a3bcc,0x3b7b3ba6,0x3b073b58,0x3b0a3b47,0x3a3a3aa8,0x3a7b3ac6,0x393939bf,0x39cf3a28,0x380b38a7,0x3908396e,0x357936cf,0x382c389d,0x315a3417,
0x3bf53bff,0x3bec3bfe,0x3bc53be2,0x3b933bc8,0x3b6e3b9e,0x3af73b4d,0x3af43b35,0x3a1c3a91,0x3a573aa9,0x390b399a,0x399c39fd,0x37993871,0x38c53934,0x34d8363f,0x37af3851,0x2fb032cc,
0x3bf43bff,0x3beb3bfe,0x3bbf3bdf,0x3b8c3bc5,0x3b613b95,0x3ae53b41,0x3adc3b23,0x39fd3a79,0x3a323a8b,0x38dc3973,0x396739d1,0x37183839,0x388038f7,0x343535ae,0x37023803,0x2ca93166,
0x3be93bfd,0x3bdd3bfc,0x3b853bc1,0x3b413b9e,0x3ad43b35,0x3a343ac8,0x39de3a61,0x38c53988,0x38ac394b,0x361737e0,0x36963800,0x30863435,0x3322351a,0xaecf2484,0x267b2ffb,0xb590b352,
0x3be83bfd,0x3bdb3bfc,0x3b7d3bbd,0x3b383b99,0x3ac13b29,0x3a1e3ab9,0x39bd3a48,0x389f396a,0x387b3923,0x35a83783,0x3611378e,0x2ecf336b,0x31d53484,0xb0b8a54d,0xa5b22d26,0xb645b45a,
0x3be63bfd,0x3bd93bfc,0x3b753bb9,0x3b2e3b94,0x3aaf3b1c,0x3a083aa9,0x399c3a2e,0x3878394b,0x384938fa,0x35373724,0x358a3718,0x2c903269,0x308633d9,0xb207ab8e,0xac77289d,0xb6f6b508,
0x3be53bfd,0x3bd73bfb,0x3b6d3bb5,0x3b253b8f,0x3a9b3b0f,0x39f13a9a,0x397a3a14,0x3851392d,0x381638cf,0x34c636c3,0x350236a1,0x289d3166,0x2e6b32a7,0xb352ae39,0xaf7ea052,0xb7a4b5b3,
0x3be33bfd,0x3bd53bfb,0x3b653bb0,0x3b1b3b8a,0x3a883b01,0x39d93a8a,0x395739f9,0x3829390d,0x37c538a4,0x34543662,0x34783628,0x12483061,0x2b8e3172,0xb44eb055,0xb141aac5,0xb826b65c,
0x3be23bfd,0x3bd33bfb,0x3b5c3bac,0x3b103b85,0x3a733af4,0x39c13a79,0x393439de,0x380038ed,0x375c3878,0x33c035ff,0x33d935ae,0xa86b2eb6,0x2484303c,0xb4f0b18b,0xb2bfae39,0xb878b702,
0x3be03bfc,0x3bd13bfb,0x3b533ba7,0x3b063b7f,0x3a5f3ae5,0x39a93a68,0x391039c1,0x37af38cd,0x36f1384c,0x32d8359c,0x32bf3531,0xac772ca9,0xa6162e07,0xb590b2bf,0xb41db086,0xb8c8b7a4,
0x3bde3bfc,0x3bcf3bfb,0x3b4b3ba3,0x3afb3b7a,0x3a4a3ad7,0x39913a57,0x38eb39a5,0x375c38ac,0x3684381e,0x31ee3537,0x31a434b4,0xaeb62934,0xac2b2b2a,0xb62eb3f1,0xb4d8b1ee,0xb914b821,
0x3bcd3bfa,0x3bbb3bf8,0x3af03b74,0x3a933b43,0x39783a46,0x38a239b0,0x3707388b,0x344736e0,0x310334d2,0xacdb2e39,0xb07a2052,0xb690b3e5,0xb6c9b490,0xb991b87e,0xb95eb86e,0xbb30ba79,
0x3bcb3bfa,0x3bb93bf8,0x3ae53b6e,0x3a863b3c,0x395e3a34,0x3885399c,0x36b23869,0x33d93696,0x3016346c,0xaeb62c90,0xb197a616,0xb713b472,0xb761b526,0xb9ccb8be,0xb9a5b8b9,0xbb58baad,
0x3bc93bfa,0x3bb63bf8,0x3ada3b68,0x3a793b35,0x39443a22,0x38693988,0x365c3846,0x3322364b,0x2e523405,0xb04829ca,0xb2b3ab2a,0xb793b4f0,0xb7f6b5b9,0xba05b8fc,0xb9e8b901,0xbb7dbadd,
0x3bc73bfa,0x3bb43bf7,0x3acf3b62,0x3a6c3b2e,0x392a3a10,0x384c3973,0x36053824,0x326935ff,0x2c77333a,0xb13424e9,0xb3cdada3,0xb809b56d,0xb844b64b,0xba3cb939,0xba28b947,0xbb9dbb0a,
0x3bc53bf9,0x3bb13bf7,0x3ac33b5c,0x3a5f3b27,0x391039fd,0x382e395e,0x35ae3800,0x31b035b3,0x29343269,0xb21f9f12,0xb472afb0,0xb846b5e8,0xb88bb6da,0xba70b973,0xba65b98a,0xbbb9bb34,
0x3bc23bf9,0x3baf3bf7,0x3ab73b56,0x3a513b20,0x38f539ea,0x38113949,0x355537ba,0x30f63567,0x21e43197,0xb309a839,0xb4fcb0de,0xb883b662,0xb8cfb767,0xbaa1b9ab,0xba9db9ca,0xbbd0bb5a,
0x3bc03bf9,0x3bac3bf7,0x3aab3b50,0x3a443b19,0x38d939d7,0x37e63934,0x34fc3772,0x303c351a,0xa48430c5,0xb3f1ab8e,0xb584b1e2,0xb8beb6da,0xb912b7f1,0xbacfb9e2,0xbad2ba08,0xbbe3bb7c,
0x3bbe3bf9,0x3ba93bf6,0x3a9f3b49,0x3a363b12,0x38be39c4,0x37a9391e,0x34a23729,0x2f0134cc,0xa9fd2fe2,0xb46cad71,0xb60bb2e4,0xb8f7b750,0xb953b83c,0xbafaba16,0xbb03ba42,0xbbf1bb9a,
0x96488000,0xa6ad8000,0x9cb69a48,0xad00aaac,0x9fdb9e48,0xb029aeaa,0xa17fa0b6,0xb1cfb0fd,0xa311a248,0xb371b2a1,0xa452a3db,0xb487b420,0xa51ba4b6,0xb552b4ed,0xa5e4a57f,0xb61ab5b6,
0x9cb68000,0xa7768000,0xa311a0b6,0xad97ab75,0xa5e4a4b6,0xb0a6af72,0xa81fa711,0xb27cb191,0xa94da8b6,0xb426b365,0xaa7aa9e3,0xb50bb499,0xaba7ab11,0xb5ebb57c,0xac6aac1f,0xb6c6b659,
0x9fdb8000,0xa81f8000,0xa5e4a3db,0xae2dac1f,0xa8e8a7da,0xb122b01d,0xaadea9e3,0xb328b226,0xac6aabd9,0xb493b414,0xad65ace7,0xb58db511,0xae5fade2,0xb682b608,0xaf59aedc,0xb76fb6f9,
0xa17f8000,0xa8848000,0xa81fa57f,0xaec3ac83,0xaadea97f,0xb19eb080,0xacceac1f,0xb3d3b2b9,0xae2dad7e,0xb4ffb475,0xaf8baedc,0xb60eb587,0xb074b01d,0xb715b693,0xb122b0cb,0xb80ab796,
0xa3118000,0xa8e88000,0xa94da711,0xaf59ace7,0xac6aab11,0xb219b0e4,0xae2dad4c,0xb43eb34c,0xafefaf0e,0xb56ab4d5,0xb0d7b067,0xb68db5fd,0xb1b6b147,0xb7a6b71b,0xb294b226,0xb85ab817,
0xa4528000,0xa94d8000,0xaa7aa852,0xafefad4c,0xad65ac51,0xb294b147,0xaf8bae78,0xb493b3df,0xb0d7b04e,0xb5d4b534,0xb1e8b160,0xb70ab670,0xb2f7b26f,0xb81ab7a1,0xb402b37d,0xb8a8b862,
0xa51b8000,0xa9b18000,0xaba7a91b,0xb042adb0,0xae5fad1a,0xb30fb1aa,0xb074afa4,0xb4e7b438,0xb1b6b115,0xb63cb593,0xb2f7b257,0xb785b6e3,0xb41ab396,0xb85fb812,0xb4b7b469,0xb8f3b8ab,
0xa5e48000,0xaa168000,0xac6aa9e3,0xb08dae14,0xaf59ade2,0xb389b20d,0xb122b067,0xb53ab481,0xb294b1db,0xb6a4b5f1,0xb402b34c,0xb7feb753,0xb4b7b45d,0xb8a3b852,0xb56ab511,0xb93cb8f1,
0xaa7a8000,0xacce8000,0xb0d7ae78,0xb328b0cb,0xb402b26f,0xb5dfb4bd,0xb58db4c9,0xb805b6f9,0xb70ab64e,0xb902b887,0xb83ab7c2,0xb9e3b976,0xb8e5b891,0xbaa2ba47,0xb982b935,0xbb3abaf3,
0xaade8000,0xad008000,0xb122aedc,0xb371b0fd,0xb43eb2d2,0xb61ab4ed,0xb5dfb511,0xb82ab73d,0xb76fb6aa,0xb92eb8b0,0xb874b817,0xba11b9a4,0xb924b8ce,0xbaceba74,0xb9c5b976,0xbb60bb1d,
0xab438000,0xad338000,0xb16caf40,0xb3bab12e,0xb47bb334,0xb654b51d,0xb631b558,0xb850b780,0xb7d2b705,0xb958b8d8,0xb8adb84d,0xba3db9d0,0xb962b909,0xbaf7baa0,0xba04b9b5,0xbb83bb43,
0xaba78000,0xad658000,0xb1b6afa4,0xb402b160,0xb4b7b396,0xb68db54c,0xb682b59f,0xb874b7c2,0xb81ab75e,0xb982b900,0xb8e5b881,0xba67b9fa,0xb99db943,0xbb1ebac9,0xba41b9f2,0xbba1bb67,
0xac068000,0xad978000,0xb201b004,0xb426b191,0xb4f3b3f7,0xb6c6b57c,0xb6d2b5e5,0xb899b802,0xb84ab7b7,0xb9aab927,0xb91bb8b5,0xba90ba23,0xb9d6b97b,0xbb42baf0,0xba7aba2b,0xbbbcbb86,
0xac388000,0xadc98000,0xb24bb036,0xb44bb1c3,0xb52fb42c,0xb6ffb5ab,0xb721b62b,0xb8bcb822,0xb87ab807,0xb9d2b94d,0xb94fb8e7,0xbab6ba4b,0xba0db9b1,0xbb63bb14,0xbab0ba62,0xbbd2bba2,
0xac6a8000,0xadfb8000,0xb294b067,0xb46fb1f4,0xb56ab45d,0xb737b5da,0xb76fb670,0xb8e0b842,0xb8a8b832,0xb9f8b972,0xb982b918,0xbadbba71,0xba41b9e5,0xbb81bb36,0xbae1ba95,0xbbe3bbbb,
0xac9c8000,0xae2d8000,0xb2deb099,0xb493b226,0xb5a5b48d,0xb76fb608,0xb7bdb6b5,0xb902b862,0xb8d6b85d,0xba1db996,0xb9b3b948,0xbafeba95,0xba73ba17,0xbb9cbb55,0xbb10bac6,0xbbf1bbd0,
0xae5f8000,0xafef8000,0xb4b7b257,0xb5d4b3df,0xb7a6b637,0xb8a8b7a1,0xb924b881,0xba1db96d,0xba41b9ba,0xbb32bab5,0xbb1ebab8,0xbbd6bb93,0xbbb3bb72,0xbbfebbf9,0xbbfabbe1,0xbba9bbe3,
0xae918000,0xb0108000,0xb4dbb288,0xb5f7b408,0xb7ddb665,0xb8c1b7cd,0xb946b8a0,0xba39b989,0xba64b9dc,0xbb4abad0,0xbb3dbad9,0xbbe2bba6,0xbbc8bb8c,0xbbf9bbfe,0xbbffbbee,0xbb8bbbd2,
0xaec38000,0xb0298000,0xb4ffb2b9,0xb61ab420,0xb80ab693,0xb8dbb7f9,0xb966b8bf,0xba54b9a4,0xba85b9fe,0xbb60bae9,0xbb59baf9,0xbbedbbb7,0xbbd9bba4,0xbbf0bc00,0xbc00bbf8,0xbb6abbbe,
0xaef58000,0xb0428000,0xb523b2ea,0xb63cb438,0xb825b6c1,0xb8f3b812,0xb986b8dd,0xba6fb9be,0xbaa5ba1f,0xbb76bb02,0xbb73bb17,0xbbf5bbc7,0xbbe7bbb9,0xbbe4bbff,0xbbfcbbfe,0xbb45bba6,
0xaf278000,0xb05b8000,0xb546b31b,0xb65fb451,0xb840b6ee,0xb90cb828,0xb9a6b8fb,0xba89b9d8,0xbac4ba3f,0xbb89bb1a,0xbb8bbb33,0xbbfbbbd5,0xbbf2bbcb,0xbbd6bbfb,0xbbf4bc00,0xbb1bbb8a,
0xaf598000,0xb0748000,0xb56ab34c,0xb682b469,0xb85ab71b,0xb924b83d,0xb9c5b918,0xbaa2b9f2,0xbae1ba5e,0xbb9cbb30,0xbba1bb4e,0xbbffbbe1,0xbbfabbdb,0xbbc3bbf5,0xbbe7bbfe,0xbaeebb6b,
0xaf8b8000,0xb08d8000,0xb58db37d,0xb6a4b481,0xb874b748,0xb93cb852,0xb9e3b935,0xbababa0b,0xbafeba7c,0xbbacbb46,0xbbb5bb67,0xbc00bbeb,0xbbffbbe8,0xbbaebbec,0xbbd7bbf9,0xbabdbb49,
0xafbd8000,0xb0a68000,0xb5b1b3ae,0xb6c6b499,0xb88eb775,0xb954b867,0xba00b951,0xbad1ba23,0xbb18ba99,0xbbbcbb5a,0xbbc6bb7d,0xbbffbbf3,0xbc00bbf2,0xbb96bbe0,0xbbc2bbf0,0xba89bb22,
0xb0be8000,0xb1858000,0xb6e8b4b1,0xb7f3b570,0xb96bb87c,0xba19b91d,0xbae8ba3b,0xbb7fbae6,0xbbc9bb6e,0xbc00bbdd,0xbbfcbbf9,0xbb8ebbe5,0xbb7abbd1,0xba35bafc,0xba50baf9,0xb820b93e,
0xb0d78000,0xb19e8000,0xb70ab4c9,0xb80ab587,0xb982b891,0xba2db930,0xbafeba52,0xbb8ebaf9,0xbbd6bb80,0xbc00bbe6,0xbbf6bbfd,0xbb76bbda,0xbb5cbbc0,0xba00bad6,0xba15bacc,0xb79bb8fb,
0xb0f08000,0xb1b68000,0xb72cb4e1,0xb81ab59f,0xb999b8a6,0xba41b943,0xbb13ba69,0xbb9cbb0b,0xbbe0bb91,0xbbfebbed,0xbbeebc00,0xbb5cbbcd,0xbb3abbab,0xb9c9baae,0xb9d6ba9c,0xb6f4b8b5,
0xb1098000,0xb1cf8000,0xb74eb4f9,0xb82ab5b6,0xb9afb8ba,0xba54b956,0xbb27ba7f,0xbba9bb1d,0xbbe9bba0,0xbbfbbbf4,0xbbe3bc00,0xbb3fbbbe,0xbb16bb95,0xb990ba83,0xb994ba69,0xb648b86d,
0xb1228000,0xb1e88000,0xb76fb511,0xb83ab5ce,0xb9c5b8ce,0xba67b969,0xbb3aba95,0xbbb5bb2e,0xbbf1bbaf,0xbbf6bbf8,0xbbd7bbfe,0xbb21bbad,0xbaeebb7b,0xb954ba56,0xb94fba33,0xb599b822,
0xb13b8000,0xb2018000,0xb790b529,0xb84ab5e5,0xb9dab8e2,0xba7ab97b,0xbb4cbaaa,0xbbc0bb3e,0xbbf7bbbc,0xbbefbbfc,0xbbc8bbfb,0xbb01bb9b,0xbac4bb5f,0xb916ba27,0xb907b9fa,0xb4e7b7ac,
0xb1538000,0xb2198000,0xb7b2b540,0xb85ab5fd,0xb9f0b8f6,0xba8cb98d,0xbb5ebabf,0xbbcbbb4e,0xbbfcbbc9,0xbbe7bbff,0xbbb7bbf6,0xbadebb86,0xba97bb41,0xb8d6b9f6,0xb8bcb9be,0xb432b710,
0xb16c8000,0xb2328000,0xb7d2b558,0xb86ab614,0xba04b909,0xba9eb99f,0xbb6fbad3,0xbbd4bb5d,0xbbfebbd4,0xbbdebc00,0xbba3bbee,0xbababb70,0xba67bb20,0xb894b9c3,0xb86fb980,0xb2f7b670,
0x98b69248,0xa901a2ad,0x9d7f9bdb,0xadd5ac2b,0xa0529f12,0xb093af7e,0xa1e4a11b,0xb238b166,0xa376a2ad,0xb3d9b309,0xa484a420,0xb4bab454,0xa54da4e9,0xb584b520,0xa616a5b2,0xb64bb5e8,
0x9f1298b6,0xa998a376,0xa420a1e4,0xae84aca9,0xa67ba54d,0xb11cb02f,0xa86ba7a8,0xb2f0b207,0xa998a901,0xb460b3d9,0xaac5aa2f,0xb543b4d2,0xabf2ab5c,0xb622b5b3,0xac90ac44,0xb6fcb690,
0xa1e49bdb,0xaa2fa420,0xa6dfa4e9,0xaf33ad26,0xa966a86b,0xb1a4b09f,0xab5caa61,0xb3a8b2a7,0xaca9ac2b,0xb4d2b454,0xada3ad26,0xb5cbb54f,0xae9dae20,0xb6beb645,0xaf97af1a,0xb7a9b734,
0xa4209d7f,0xaac5a484,0xa8cfa6df,0xafe2ada3,0xab8eaa2f,0xb22cb10f,0xad26ac77,0xb42fb346,0xae84add5,0xb543b4ba,0xafe2af33,0xb651b5cb,0xb09fb048,0xb756b6d4,0xb14db0f6,0xb829b7d5,
0xa54d9f12,0xab5ca4e9,0xaa2fa86b,0xb048ae20,0xacdbabf2,0xb2b3b17f,0xae9dadbc,0xb48ab3e5,0xb02faf7e,0xb5b3b520,0xb10fb09f,0xb6d4b645,0xb1eeb17f,0xb7ebb761,0xb2ccb25d,0xb87bb839,
0xa67ba052,0xabf2a54d,0xab8ea966,0xb09fae9d,0xadeeacdb,0xb33ab1ee,0xb00aaf01,0xb4e4b441,0xb11cb093,0xb622b584,0xb22cb1a4,0xb756b6be,0xb33ab2b3,0xb83eb7eb,0xb423b3c0,0xb8cab885,
0xa7a8a11b,0xac44a5b2,0xac77aa61,0xb0f6af1a,0xaf01adbc,0xb3c0b25d,0xb0c5b023,0xb53db490,0xb207b166,0xb690b5e8,0xb346b2a7,0xb7d5b734,0xb441b3e5,0xb885b839,0xb4deb490,0xb917b8cf,
0xa86ba1e4,0xac90a616,0xad26ab5c,0xb14daf97,0xb00aae9d,0xb423b2cc,0xb17fb0c5,0xb596b4de,0xb2f0b238,0xb6fcb64b,0xb42fb3a8,0xb829b7a9,0xb4e4b48a,0xb8cab87b,0xb596b53d,0xb961b917,
0xacdba67b,0xaf33a8cf,0xb1a4b00a,0xb429b1fa,0xb466b33a,0xb66db54f,0xb5eeb52c,0xb846b783,0xb767b6ad,0xb93db8c5,0xb866b80e,0xba16b9ae,0xb90db8bb,0xbacbba75,0xb9a7b95c,0xbb5abb18,
0xad26a6df,0xaf7ea901,0xb1fab048,0xb454b238,0xb4a8b3a8,0xb6adb584,0xb645b579,0xb86eb7ca,0xb7d0b70d,0xb96ab8f0,0xb8a2b846,0xba44b9db,0xb94eb8fa,0xbaf7baa2,0xb9eab99e,0xbb7ebb40,
0xad71a744,0xafc9a934,0xb251b086,0xb47eb276,0xb4eab40b,0xb6ebb5b9,0xb69bb5c5,0xb895b809,0xb81cb76c,0xb995b919,0xb8dcb87e,0xba70ba08,0xb98cb936,0xbb1fbacd,0xba2ab9de,0xbb9ebb65,
0xadbca7a8,0xb00aa966,0xb2a7b0c5,0xb4a8b2b3,0xb52cb441,0xb729b5ee,0xb6f1b611,0xb8bbb82c,0xb84eb7ca,0xb9bfb942,0xb914b8b4,0xba9aba32,0xb9c8b971,0xbb44baf5,0xba66ba1a,0xbbbabb86,
0xae07a806,0xb02fa998,0xb2fdb103,0xb4d2b2f0,0xb56db478,0xb767b622,0xb745b65c,0xb8e1b84e,0xb880b813,0xb9e8b96a,0xb94bb8e8,0xbac1ba5b,0xba01b9a9,0xbb66bb1b,0xba9fba53,0xbbd1bba3,
0xae52a839,0xb055a9ca,0xb352b141,0xb4fcb32e,0xb5aeb4ae,0xb7a4b656,0xb799b6a7,0xb906b871,0xb8b1b841,0xba10b991,0xb981b91c,0xbae7ba82,0xba38b9e0,0xbb85bb3d,0xbad4ba8a,0xbbe3bbbc,
0xae9da86b,0xb07aa9fd,0xb3a8b17f,0xb526b36b,0xb5eeb4e4,0xb7e0b68a,0xb7ebb6f1,0xb92ab892,0xb8e1b86e,0xba36b9b7,0xb9b4b94e,0xbb0abaa8,0xba6cba14,0xbba0bb5d,0xbb04babc,0xbbf1bbd1,
0xaee8a89d,0xb09faa2f,0xb3fdb1bd,0xb54fb3a8,0xb62eb51a,0xb80eb6be,0xb81eb73a,0xb94eb8b4,0xb910b89a,0xba5bb9db,0xb9e6b97e,0xbb2cbacb,0xba9dba46,0xbbb8bb7b,0xbb31baec,0xbbfbbbe3,
0xb0c5aa61,0xb1eeabf2,0xb579b3e5,0xb6beb4e4,0xb82cb6f1,0xb90db83e,0xb971b8d4,0xba6cb9c8,0xba7fb9ff,0xbb66baf7,0xbb4bbaed,0xbbebbbb8,0xbbcdbb95,0xbbf4bc00,0xbbffbbf0,0xbb80bbca,
0xb0eaaa93,0xb213ac12,0xb5a2b411,0xb6e5b502,0xb849b724,0xb928b856,0xb993b8f5,0xba88b9e4,0xbaa1ba22,0xbb7cbb10,0xbb67bb0d,0xbbf4bbc8,0xbbdebbad,0xbbeabc00,0xbbffbbf9,0xbb5cbbb3,
0xb10faac5,0xb238ac2b,0xb5cbb42f,0xb70db520,0xb866b756,0xb942b86e,0xb9b4b914,0xbaa2b9ff,0xbac1ba44,0xbb90bb29,0xbb81bb2c,0xbbfbbbd6,0xbbebbbc1,0xbbdbbbfc,0xbbfbbbff,0xbb34bb98,
0xb134aaf8,0xb25dac44,0xb5f4b44e,0xb734b53d,0xb883b788,0xb95cb885,0xb9d5b934,0xbabcba1a,0xbae1ba65,0xbba3bb40,0xbb99bb48,0xbbffbbe3,0xbbf6bbd3,0xbbcabbf6,0xbbf2bc00,0xbb07bb7a,
0xb15aab2a,0xb282ac5e,0xb61db46c,0xb75cb55b,0xb89fb7ba,0xb975b89d,0xb9f5b953,0xbad5ba34,0xbafeba84,0xbbb4bb56,0xbbafbb62,0xbc00bbed,0xbbfcbbe2,0xbbb5bbed,0xbbe4bbfd,0xbad7bb57,
0xb17fab5c,0xb2a7ac77,0xb645b48a,0xb783b579,0xb8bbb7eb,0xb98eb8b4,0xba14b971,0xbaedba4e,0xbb1bbaa2,0xbbc3bb6b,0xbbc1bb7b,0xbbffbbf5,0xbc00bbee,0xbb9cbbe1,0xbbd2bbf6,0xbaa2bb31,
0xb1a4ab8e,0xb2ccac90,0xb66db4a8,0xb7a9b596,0xb8d7b80e,0xb9a7b8ca,0xba32b98e,0xbb04ba66,0xbb35bac0,0xbbd1bb7e,0xbbd2bb91,0xbbfbbbfb,0xbbffbbf7,0xbb80bbd2,0xbbbbbbeb,0xba6abb07,
0xb1c9abc0,0xb2f0aca9,0xb696b4c6,0xb7d0b5b3,0xb8f2b826,0xb9bfb8e1,0xba4fb9ab,0xbb1bba7f,0xbb4ebadc,0xbbddbb90,0xbbe0bba6,0xbbf5bbfe,0xbbfcbbfd,0xbb61bbc0,0xbba0bbdd,0xba2ebada,
0xb315acc2,0xb41dad8a,0xb7f6b5d1,0xb890b6b8,0xb9d7b8f7,0xba86b9a0,0xbb30ba96,0xbbb5bb39,0xbbe7bba1,0xbbfabbf6,0xbbecbc00,0xbb4cbbc1,0xbb3fbbab,0xb9bfba9f,0xb9efbaa9,0xb707b8b4,
0xb33aacdb,0xb42fada3,0xb80eb5ee,0xb8a2b6d4,0xb9efb90d,0xba9ab9b4,0xbb44baad,0xbbc1bb4b,0xbbefbbb0,0xbbf5bbfb,0xbbe0bbff,0xbb2dbbaf,0xbb19bb93,0xb983ba72,0xb9abba75,0xb656b869,
0xb35facf4,0xb441adbc,0xb821b60b,0xb8b4b6f1,0xba05b923,0xbaadb9c8,0xbb57bac3,0xbbcdbb5b,0xbbf6bbbe,0xbbeebbfe,0xbbd3bbfd,0xbb0cbb9c,0xbaf0bb78,0xb944ba42,0xb965ba3e,0xb5a2b81c,
0xb383ad0d,0xb454add5,0xb834b628,0xb8c5b70d,0xba1cb939,0xbac0b9db,0xbb69bad9,0xbbd6bb6b,0xbbfbbbcb,0xbbe5bc00,0xbbc2bbf8,0xbae9bb87,0xbac5bb5b,0xb903ba10,0xb91cba03,0xb4eab799,
0xb3a8ad26,0xb466adee,0xb846b645,0xb8d7b729,0xba32b94e,0xbad2b9ef,0xbb7bbaed,0xbbdfbb7a,0xbbfebbd6,0xbbdabc00,0xbbafbbf1,0xbac3bb6f,0xba96bb3b,0xb8c0b9db,0xb8cfb9c6,0xb42fb6f6,
0xb3cdad3f,0xb478ae07,0xb859b662,0xb8e8b745,0xba48b963,0xbae4ba01,0xbb8bbb01,0xbbe7bb88,0xbc00bbe0,0xbbcebbff,0xbb9abbe8,0xba9bbb56,0xba65bb18,0xb87bb9a5,0xb880b985,0xb2e4b651,
0xb3f1ad58,0xb48aae20,0xb86bb67f,0xb8fab761,0xba5db978,0xbaf5ba14,0xbb9abb15,0xbbeebb95,0xbc00bbe9,0xbbc0bbfc,0xbb82bbdd,0xba72bb3b,0xba30baf2,0xb834b96c,0xb82eb942,0xb166b5a8,
0xb40bad71,0xb49cae39,0xb87eb69b,0xb90bb77d,0xba72b98c,0xbb06ba26,0xbba8bb27,0xbbf4bba2,0xbbfebbf0,0xbbb0bbf9,0xbb68bbd0,0xba46bb1d,0xb9f9baca,0xb7d5b931,0xb7b4b8fc,0xafc9b4fc,
0x39b839ba,0x3a973ab5,0x39b339b5,0x3a583a78,0x39af39b1,0x3a153a37,0x39aa39ad,0x39cd39f2,0x39a639a8,0x398239a8,0x39a139a4,0x3933395b,0x399d399f,0x38e03909,0x3999399b,0x388938b5,
0xb979b972,0xb865b832,0xb986b980,0xb8c7b896,0xb994b98d,0xb924b8f6,0xb9a1b99b,0xb97db951,0xb9afb9a8,0xb9d2b9a8,0xb9bcb9b5,0xba21b9fa,0xb9c9b9c3,0xba6bba47,0xb9d6b9d0,0xbab0ba8e,
0xb9f4b9fe,0xbac7bae9,0xb9dfb9e9,0xba7ebaa3,0xb9c9b9d4,0xba2dba56,0xb9b3b9be,0xb9d6ba02,0xb99db9a8,0xb979b9a8,0xb986b992,0xb916b948,0xb970b97b,0xb8adb8e2,0xb958b964,0xb840b877,
0x39373927,0x381a37b7,0x39583948,0x38943858,0x39793969,0x390738ce,0x39993989,0x3974393e,0x39b839a8,0x39da39a8,0x39d639c7,0x3a393a0b,0x39f439e5,0x3a903a65,0x3a113a02,0x3ade3ab8,
0x3a2d3a3f,0x3af43b1a,0x3a093a1b,0x3aa23acc,0x39e339f6,0x3a453a74,0x39bc39d0,0x39df3a13,0x399439a8,0x397039a8,0x396b3980,0x38f83935,0x39413956,0x387a38ba,0x3916392b,0x37e83838,
0xb8f3b8d8,0xb79bb705,0xb929b90e,0xb85fb817,0xb95db943,0xb8eab8a6,0xb990b976,0xb96bb92b,0xb9c0b9a8,0xb9e3b9a8,0xb9f0b9d8,0xba50ba1b,0xba1dba07,0xbab3ba83,0xba49ba33,0xbb0abae0,
0xba64ba7c,0xbb1ebb46,0xba31ba4b,0xbac4baf3,0xb9fcba17,0xba5cba92,0xb9c5b9e1,0xb9e7ba23,0xb98bb9a8,0xb966b9a8,0xb94fb96d,0xb8dbb922,0xb911b930,0xb845b891,0xb8d1b8f1,0xb74eb7ee,
0x38ad3887,0x36ff364e,0x38f838d3,0x382a37ac,0x3941391d,0x38cc387c,0x39863964,0x39623918,0x39c939a8,0x39eb39a8,0x3a0939e9,0x3a673a2b,0x3a453a27,0x3ad53aa0,0x3a7e3a62,0x3b323b05,
0x3b453b6e,0x3bbc3bdd,0x3ae53b17,0x3b573b8f,0x3a733aae,0x3ac73b14,0x39f03a33,0x3a113a71,0x395d39a8,0x393739a8,0x38bc390e,0x384038bf,0x380f3867,0x365f3775,0x36af376a,0x341a3540,
0xb65fb593,0xb389b115,0xb7e8b726,0xb625b4f9,0xb8adb852,0xb830b748,0xb958b905,0xb933b8b5,0xb9f4b9a8,0xba15b9a8,0xba7eba3b,0xbad1ba78,0xbaf4babc,0xbb63bb20,0xbb57bb28,0xbbc6bb9b,
0xbb68bb91,0xbbd0bbed,0xbb04bb39,0xbb6fbba6,0xba89bac9,0xbadbbb2b,0xb9f8ba43,0xba19ba7f,0xb954b9a8,0xb92eb9a8,0xb89eb8fb,0xb820b8ab,0xb7b2b83d,0xb5ebb71b,0xb60eb6e3,0xb2deb4b1,
0x35bc34d5,0x32322f0e,0x377a369e,0x35b13469,0x388e3828,0x380f36ee,0x394f38f1,0x392938a0,0x39fc39a8,0x3a1d39a8,0x3a933a4b,0x3ae53a87,0x3b133ad6,0x3b7a3b36,0x3b783b49,0x3bd93bb1,
0x3b873baf,0x3be13bf8,0x3b213b58,0x3b853bbb,0x3a9e3ae3,0x3aee3b41,0x3a003a52,0x3a213a8e,0x394a39a8,0x392439a8,0x387f38e7,0x37fe3896,0x37423812,0x357636c1,0x356a3659,0x31853420,
0xb517b414,0xb0d7abd9,0xb70ab614,0xb53ab3ae,0xb86fb7f9,0xb7ddb693,0xb946b8dd,0xb91fb88c,0xba04b9a8,0xba25b9a8,0xbaa9ba5a,0xbaf7ba95,0xbb2fbaf0,0xbb90bb4b,0xbb96bb67,0xbbe8bbc4,
0xbba3bbc9,0xbbefbbff,0xbb3dbb74,0xbb9abbcd,0xbab3bafc,0xbb01bb55,0xba09ba62,0xba29ba9c,0xb941b9a8,0xb91bb9a8,0xb85fb8d3,0xb7bdb881,0xb6d2b7cd,0xb4ffb665,0xb4c3b5ce,0xb029b31b,
0x346f32a1,0x2ef52248,0x36993587,0x34c33288,0x385037a1,0x379b3637,0x393c38c9,0x39163877,0x3a0d39a8,0x3a2d39a8,0x3abd3a69,0x3b0a3aa3,0x3b4a3b08,0x3ba33b5f,0x3bb03b82,0x3bf43bd5,
0x3bf83c00,0x3bf93bd4,0x3bac3bdc,0x3be43bfe,0x3b133b69,0x3b543bab,0x3a313aaa,0x3a503ae0,0x391139a8,0x38ea39a8,0x377a386d,0x366b3817,0x34873608,0x313b348d,0x2d9731f4,0xad65291b,
0xac3828b6,0x2ec33365,0xb44bb160,0xb0bea57f,0xb759b5da,0xb648b45d,0xb90cb862,0xb8e5b80d,0xba35b9a8,0xba54b9a8,0xbb1bbab1,0xbb5cbae6,0xbbb5bb72,0xbbe9bbb2,0xbbfcbbe3,0xbbf5bc00,
0xbbfebbfc,0xbbefbbbc,0xbbbdbbe9,0xbbeebc00,0xbb24bb7b,0xbb63bbb9,0xba39bab8,0xba58baed,0xb907b9a8,0xb8e0b9a8,0xb737b858,0xb625b802,0xb40eb5ab,0xb042b42c,0xa9b1b0cb,0x30109a48,
0x25e4ad7e,0xb0beb475,0x33a23036,0x2f8ba3db,0x3715357c,0x360233f7,0x3902384d,0x38db37ee,0x3a3d39a8,0x3a5c39a8,0x3b2c3abf,0x3b6a3af3,0x3bc53b84,0x3bf23bc0,0x3bff3bee,0x3be93c00,
0x3c003bf4,0x3be23ba0,0x3bcc3bf3,0x3bf53bff,0x3b353b8c,0x3b713bc6,0x3a413ac6,0x3a603af9,0x38fd39a8,0x38d639a8,0x36f43842,0x35df37d8,0x3328354c,0x2e913396,0x16482f40,0xb16ca852,
0x251b304e,0x32193534,0xb2adae14,0xad972aac,0xb6d2b51d,0xb5bcb334,0xb8f8b838,0xb8d1b7c2,0xba45b9a8,0xba64b9a8,0xbb3dbacc,0xbb78baff,0xbbd3bb95,0xbbf8bbcb,0xbc00bbf7,0xbbdabbfd,
0xbbfebbe6,0xbbd2bb80,0xbbd9bbfa,0xbbfbbbfb,0xbb45bb9d,0xbb7fbbd1,0xba49bad3,0xba67bb05,0xb8f3b9a8,0xb8ccb9a8,0xb6afb82d,0xb599b7ac,0xb232b4ed,0xac9cb2d2,0x294dace7,0x32c62c83,
0xac06b1db,0xb371b5f1,0x31b62b75,0x2b43adb0,0x368d34bd,0x3576326f,0x38ee3822,0x38c73796,0x3a4d39a8,0x3a6b39a8,0x3b4c3ad9,0x3b853b0b,0x3bdf3ba4,0x3bfd3bd6,0x3bfc3bfd,0x3bc83bf8,
0x3bbd3b5a,0x3b473a99,0x3bfe3bf4,0x3bf93bbe,0x3b8b3bdb,0x3bb83bf7,0x3a6f3b11,0x3a8c3b3e,0x38c139a8,0x389939a8,0x35523780,0x343236cc,0x294d320d,0xad332de2,0xb40eaedc,0xb6a4b408,
0x346336aa,0x36f438b0,0xa6ad3004,0x2e2d3451,0xb52fb1aa,0xb40ead1a,0xb8bcb76a,0xb894b6b5,0xba73b9a8,0xba90b9a8,0xbb92bb17,0xbbbdbb43,0xbbffbbe0,0xbbf6bbf9,0xbbb2bbf0,0xbb35bbb4,
0xbba5bb30,0xbb21ba5e,0xbc00bbeb,0xbbf3bbaa,0xbb98bbe4,0xbbc2bbfb,0xba76bb1d,0xba93bb49,0xb8b7b9a8,0xb88eb9a8,0xb50bb753,0xb3d3b69e,0xa17fb147,0x2f27ac51,0x34b73099,0x37423499,
0xb50bb75e,0xb790b900,0x9cb6b12e,0xb010b4e1,0x34e730e4,0x33892b11,0x38b2373d,0x38893687,0x3a7a39a8,0x3a9739a8,0x3b9e3b22,0x3bc63b4e,0x3c003be8,0x3bef3bfd,0x3b983be5,0x3b0d3b9e,
0x3b893b02,0x3af73a1f,0x3c003bdf,0x3beb3b93,0x3ba33bec,0x3bcb3bfe,0x3a7e3b28,0x3a9b3b53,0x38ad39a8,0x388439a8,0x34c33726,0x33403670,0xa51b3080,0xb08d297f,0xb55eb1c3,0xb7ddb529,
0x35b13807,0x3815394d,0x28843257,0x31093570,0xb49fb01d,0xb2f7a7da,0xb8a8b710,0xb87fb659,0xba81b9a8,0xba9eb9a8,0xbba9bb2e,0xbbcfbb58,0xbbffbbef,0xbbe6bbff,0xbb7abbd7,0xbae1bb86,
0xbb6abad0,0xbacbb9dc,0xbbfdbbd0,0xbbe1bb79,0xbbaebbf2,0xbbd3bc00,0xba85bb33,0xbaa2bb5d,0xb8a3b9a8,0xb87ab9a8,0xb47bb6f9,0xb2adb642,0x2a7aaf72,0x3185a4b6,0x360232ea,0x383a35b6,
0xb654b85d,0xb85fb996,0xac38b37d,0xb201b5fd,0x34572eaa,0x32631e48,0x389e36e3,0x3874362b,0x3a8939a8,0x3aa539a8,0x3bb33b39,0x3bd73b62,0x3bfc3bf5,0x3bdc3c00,0x3b593bc7,0x3ab33b6b,
0x39b739b9,0x3a883aa6,0x39b239b4,0x3a483a68,0x39ae39b0,0x3a033a26,0x39a939ab,0x39bb39e0,0x39a539a7,0x396e3995,0x39a039a3,0x391e3947,0x399c399e,0x38ca38f5,0x3997399a,0x3873389f,
0xb97cb975,0xb87eb84c,0xb98ab983,0xb8deb8ae,0xb997b991,0xb93bb90d,0xb9a5b99e,0xb993b967,0xb9b2b9ab,0xb9e6b9bd,0xb9bfb9b9,0xba34ba0e,0xb9ccb9c6,0xba7dba59,0xb9d9b9d3,0xbac0ba9f,
0xb9efb9f9,0xbab6bad9,0xb9d9b9e4,0xba6aba91,0xb9c4b9cf,0xba18ba42,0xb9aeb9b9,0xb9bfb9ec,0xb997b9a3,0xb961b991,0xb981b98c,0xb8fcb92f,0xb96ab975,0xb892b8c8,0xb953b95e,0xb824b85c,
0x3940392f,0x383937f6,0x39613950,0x38b13876,0x39813971,0x392338eb,0x39a03991,0x398e395a,0x39bf39b0,0x39f339c1,0x39de39cf,0x3a4f3a22,0x39fb39ec,0x3aa43a7b,0x3a183a0a,0x3af03acb,
0x3a243a36,0x3ae13b07,0x39ff3a12,0x3a8b3ab7,0x39d939ec,0x3a2c3a5d,0x39b239c6,0x39c439f9,0x398a399e,0x3953398c,0x39613975,0x38d93917,0x3936394b,0x3859389a,0x390b3921,0x37a43816,
0xb901b8e6,0xb7e6b750,0xb936b91c,0xb883b83c,0xb96ab950,0xb90bb8c8,0xb99cb983,0xb98ab94b,0xb9ccb9b4,0xb9ffb9c6,0xb9fbb9e4,0xba6aba36,0xba28ba12,0xbacaba9b,0xba53ba3e,0xbb1dbaf5,
0xba57ba70,0xbb09bb33,0xba24ba3e,0xbaabbadc,0xb9efba0a,0xba40ba77,0xb9b7b9d3,0xb9c8ba05,0xb97cb99a,0xb944b988,0xb940b95e,0xb8b6b8fe,0xb901b921,0xb81eb86b,0xb8c0b8e1,0xb6fcb79e,
0x38c0389a,0x375636a7,0x390b38e6,0x38543800,0x3953392f,0x38f238a4,0x39973975,0x3985393d,0x39d939b9,0x3a0c39ca,0x3a1839f9,0x3a843a4a,0x3a533a36,0x3aed3abb,0x3a8b3a70,0x3b473b1c,
0x3b2e3b5a,0x3ba63bce,0x3aca3afe,0x3b373b74,0x3a533a91,0x3a9d3aef,0x39cc3a12,0x39de3a42,0x39363983,0x38fc3971,0x389238e6,0x37fb3880,0x37c5383c,0x35d136eb,0x3651370d,0x330934ae,
0xb6c3b5fa,0xb460b251,0xb824b788,0xb6b8b590,0xb8d9b880,0xb873b7d5,0xb981b92f,0xb96eb8f5,0xba18b9cf,0xba48b9e0,0xba9dba5d,0xbafabaa6,0xbb0fbad9,0xbb80bb43,0xbb6cbb40,0xbbd8bbb2,
0xbb51bb7d,0xbbbdbbe0,0xbae7bb1f,0xbb4ebb8c,0xba66baa9,0xbaafbb04,0xb9d1ba1e,0xb9e2ba4e,0xb928b97e,0xb8edb96c,0xb86eb8cd,0xb7afb866,0xb74bb80b,0xb54fb684,0xb5a2b679,0xb197b411,
0x362e3549,0x338330de,0x37e6370d,0x3651350e,0x38c0385c,0x38593788,0x397c3921,0x396a38e6,0x3a2439d3,0x3a5339e4,0x3ab63a70,0x3b0f3ab7,0x3b2e3af5,0x3b973b5a,0x3b8d3b61,0x3be83bc7,
0x3b703b9c,0x3bd03bef,0x3b033b3d,0x3b653ba2,0x3a793ac1,0x3ac03b19,0x39d53a2a,0x39e63a59,0x3919397a,0x38de3967,0x384938b4,0x3761384c,0x36cf37b4,0x34cc361d,0x34f035e2,0x302332e4,
0xb596b496,0xb244aecf,0xb783b690,0xb5e8b48a,0xb8a7b836,0xb83eb73a,0xb978b912,0xb965b8d7,0xba30b9d7,0xba5fb9e8,0xbacdba82,0xbb23bac8,0xbb4cbb10,0xbbacbb6f,0xbbaabb7f,0xbbf4bbd8,
0xbb8dbbb7,0xbbe0bbf9,0xbb1dbb5a,0xbb7abbb5,0xba8bbad9,0xbad0bb2d,0xb9d9ba36,0xb9eaba65,0xb90bb975,0xb8cfb963,0xb824b89a,0xb713b831,0xb651b750,0xb447b5b3,0xb43bb549,0xad58b1a4,
0x34fc33c0,0x31032bc0,0x371e3611,0x357e3405,0x388d3811,0x382436eb,0x39733903,0x396138c8,0x3a3c39db,0x3a6a39ec,0x3ae43a94,0x3b373ad9,0x3b673b2a,0x3bbe3b83,0x3bc33b9a,0x3bfc3be7,
0x3bed3bff,0x3bff3bea,0x3b8d3bc7,0x3bcc3bf5,0x3ae13b40,0x3b1d3b83,0x39ef3a70,0x39ff3a9b,0x38c0395e,0x3883394b,0x36c33816,0x357e3750,0x33833549,0x2e84332e,0x28cf3061,0xb0aca5b2,
0xaf7ea376,0x29663166,0xb514b2fd,0xb2bfad71,0xb809b69b,0xb734b555,0xb95cb8b9,0xb949b87b,0xba75b9f1,0xbaa1ba01,0xbb49bae9,0xbb8bbb25,0xbbcfbb96,0xbbf9bbd2,0xbc00bbf2,0xbbe3bbfe,
0xbbf6bc00,0xbbfcbbda,0xbb9fbbd6,0xbbd8bbfb,0xbaf0bb52,0xbb2cbb92,0xb9f3ba7b,0xba03baa6,0xb8b1b95a,0xb873b947,0xb673b7f6,0xb52cb718,0xb276b4de,0xac5eb251,0x2052ae39,0x321f2bf2,
0x2cf4a806,0xad3fb2d8,0x34a831ee,0x31e22a93,0x37db364b,0x36fc3502,0x395738a9,0x3944386b,0x3a8039f5,0x3aab3a05,0x3b5b3af8,0x3b993b33,0x3bdd3ba7,0x3bfd3bdd,0x3bff3bfa,0x3bd13bf9,
0x3bfd3bfd,0x3bf53bc6,0x3baf3be3,0x3be23bff,0x3b003b64,0x3b393ba0,0x39f73a86,0x3a083ab0,0x38a23955,0x38633942,0x362237bf,0x34d836e0,0x31663472,0x286b3172,0xaaf82b5c,0xb390ae84,
0xa8cf2cf4,0x2fc93423,0xb43bb0de,0xb103a484,0xb7a4b5fa,0xb6c3b4ae,0xb953b89a,0xb940b85c,0xba8bb9f9,0xbab6ba0a,0xbb6cbb07,0xbba6bb40,0xbbe8bbb7,0xbc00bbe7,0xbbfabbff,0xbbbabbf1,
0xbc00bbf6,0xbbebbbae,0xbbbebbed,0xbbebbc00,0xbb0fbb74,0xbb47bbad,0xb9fbba91,0xba0cbabb,0xb892b950,0xb854b93d,0xb5d1b788,0xb484b6a7,0xb055b405,0x9248b093,0x2e6ba484,0x347e3086,
0x98b6afe2,0xb128b4d8,0x339c2f97,0x3023a420,0x376c35a8,0x368a345a,0x394e388b,0x393b384c,0x3a9639fd,0x3ac03a0e,0x3b7c3b16,0x3bb33b4d,0x3bf23bc5,0x3c003bef,0x3bf03c00,0x3ba03be5,
0x3bde3b91,0x3b8a3af7,0x3bf23bff,0x3c003be3,0x3b533bb9,0x3b823bdf,0x3a103ac5,0x3a203aec,0x38443939,0x38033925,0x342f366d,0x31b03584,0xa8392f65,0xb15a1d7f,0xb531b1c9,0xb7e0b55b,
0x3269358a,0x35a83819,0xae842a61,0x205231e2,0xb651b405,0xb567b15a,0xb936b83c,0xb923b7f6,0xbacaba12,0xbaf0ba22,0xbbbebb5a,0xbbe3bb88,0xbbfdbbf5,0xbbddbc00,0xbb81bbd6,0xbadfbb7c,
0xbbcebb70,0xbb6dbac6,0xbbf8bbfb,0xbbffbbd6,0xbb60bbc4,0xbb8dbbe7,0xba14bacf,0xba24baf5,0xb834b934,0xb7e6b921,0xb3b4b634,0xb103b549,0x2c44ada3,0x326925b2,0x35e23309,0x384135f4,
0xb3a8b63a,0xb63fb869,0x2cc2ad58,0xa89db2f0,0x3617335f,0x352c30ac,0x3931382c,0x391e37d5,0x3ad43a16,0x3afa3a26,0x3bc93b66,0x3bea3b92,0x3bf93bfa,0x3bcf3bff,0x3b5f3bc5,0x3aad3b5d,
0x3bba3b4c,0x3b4d3a93,0x3bfc3bf6,0x3bfd3bc7,0x3b6c3bce,0x3b973bed,0x3a183ad9,0x3a283afe,0x3824392f,0x37c5391c,0x330935fa,0x3055350e,0xae6b2bc0,0xb377aa61,0xb690b423,0xb890b68a,
0x347236e5,0x36d438b6,0xa9fd2f7e,0x2c1233fd,0xb5dcb2b3,0xb4f0affb,0xb92db81c,0xb919b7b4,0xbaddba1a,0xbb03ba2a,0xbbd3bb72,0xbbf0bb9c,0xbbf2bbfe,0xbbbfbbfc,0xbb38bbaf,0xba77bb3c,
0xbba4bb23,0xbb2aba5b,0xbbffbbee,0xbbfabbb6,0xbb77bbd7,0xbba1bbf3,0xba1cbae2,0xba2cbb07,0xb813b92a,0xb7a4b917,0xb25db5bf,0xaf4cb4d2,0x3048a839,0x34412cf4,0x373a34c0,0x38dc371e,
0xb50eb78e,0xb767b901,0x24e9b0d1,0xadd5b484,0x35a23207,0x34b42e9d,0x3928380b,0x39143793,0x3ae73a1e,0x3b0c3a2e,0x3bdb3b7d,0x3bf53ba6,0x3be93c00,0x3bad3bf7,0x3b0d3b97,0x3a3e3b18,
0xb999b996,0xb889b85d,0xb99db99b,0xb8e0b8b5,0xb9a1b99f,0xb933b909,0xb9a6b9a4,0xb982b95b,0xb9aab9a8,0xb9cdb9a8,0xb9afb9ad,0xba15b9f2,0xb9b3b9b1,0xba58ba37,0xb9b8b9b5,0xba97ba78,
0xb9d6b9dc,0xbab0bad0,0xb9c9b9d0,0xba6bba8e,0xb9bcb9c3,0xba21ba47,0xb9afb9b5,0xb9d2b9fa,0xb9a1b9a8,0xb97db9a8,0xb994b99b,0xb924b951,0xb986b98d,0xb8c7b8f6,0xb979b980,0xb865b896,
0x3958394d,0x38403807,0x39703964,0x38ad3877,0x3986397b,0x391638e2,0x399d3992,0x39793948,0x39b339a8,0x39d639a8,0x39c939be,0x3a2d3a02,0x39df39d4,0x3a7e3a56,0x39f439e9,0x3ac73aa3,
0x3a113a1f,0x3ade3b02,0x39f43a02,0x3a903ab8,0x39d639e5,0x3a393a65,0x39b839c7,0x39da3a0b,0x399939a8,0x397439a8,0x39793989,0x3907393e,0x39583969,0x389438ce,0x39373948,0x381a3858,
0xb916b900,0xb7e8b75e,0xb941b92b,0xb87ab838,0xb96bb956,0xb8f8b8ba,0xb994b980,0xb970b935,0xb9bcb9a8,0xb9dfb9a8,0xb9e3b9d0,0xba45ba13,0xba09b9f6,0xbaa2ba74,0xba2dba1b,0xbaf4bacc,
0xba49ba5e,0xbb0abb30,0xba1dba33,0xbab3bae0,0xb9f0ba07,0xba50ba83,0xb9c0b9d8,0xb9e3ba1b,0xb990b9a8,0xb96bb9a8,0xb95db976,0xb8eab92b,0xb929b943,0xb85fb8a6,0xb8f3b90e,0xb79bb817,
0x38d138b0,0x374e36aa,0x391138f1,0x384537ee,0x394f3930,0x38db3891,0x398b396d,0x39663922,0x39c539a8,0x39e739a8,0x39fc39e1,0x3a5c3a23,0x3a313a17,0x3ac43a92,0x3a643a4b,0x3b1e3af3,
0x3a7e3a99,0x3b323b5a,0x3a453a62,0x3ad53b05,0x3a093a27,0x3a673aa0,0x39c939e9,0x39eb3a2b,0x398639a8,0x396239a8,0x39413964,0x38cc3918,0x38f8391d,0x382a387c,0x38ad38d3,0x36ff37ac,
0xb6afb5f1,0xb41ab1db,0xb80fb76a,0xb65fb540,0xb8bcb867,0xb840b775,0xb95db90e,0xb937b8bf,0xb9f0b9a8,0xba11b9a8,0xba73ba33,0xbac7ba71,0xbae5baae,0xbb57bb14,0xbb45bb17,0xbbbcbb8f,
0xbb57bb80,0xbbc6bbe6,0xbaf4bb28,0xbb63bb9b,0xba7ebabc,0xbad1bb20,0xb9f4ba3b,0xba15ba78,0xb958b9a8,0xb933b9a8,0xb8adb905,0xb830b8b5,0xb7e8b852,0xb625b748,0xb65fb726,0xb389b4f9,
0x360e3534,0x32de304e,0x37b236e3,0x35eb34b1,0x389e383d,0x3820371b,0x395438fb,0x392e38ab,0x39f839a8,0x3a1939a8,0x3a893a43,0x3adb3a7f,0x3b043ac9,0x3b6f3b2b,0x3b683b39,0x3bd03ba6,
0x3b783ba0,0x3bd93bf4,0x3b133b49,0x3b7a3bb1,0x3a933ad6,0x3ae53b36,0x39fc3a4b,0x3a1d3a87,0x394f39a8,0x392939a8,0x388e38f1,0x380f38a0,0x377a3828,0x35b136ee,0x35bc369e,0x32323469,
0xb56ab475,0xb185ad7e,0xb742b659,0xb576b420,0xb87fb812,0xb7feb6c1,0xb94ab8e7,0xb924b896,0xba00b9a8,0xba21b9a8,0xba9eba52,0xbaeeba8e,0xbb21bae3,0xbb85bb41,0xbb87bb58,0xbbe1bbbb,
0xbb96bbbc,0xbbe8bbfc,0xbb2fbb67,0xbb90bbc4,0xbaa9baf0,0xbaf7bb4b,0xba04ba5a,0xba25ba95,0xb946b9a8,0xb91fb9a8,0xb86fb8dd,0xb7ddb88c,0xb70ab7f9,0xb53ab693,0xb517b614,0xb0d7b3ae,
0x34c33365,0x302928b6,0x36d235ce,0x34ff331b,0x385f37cd,0x37bd3665,0x394138d3,0x391b3881,0x3a0939a8,0x3a2939a8,0x3ab33a62,0x3b013a9c,0x3b3d3afc,0x3b9a3b55,0x3ba33b74,0x3bef3bcd,
0x3bb03bd4,0x3bf43c00,0x3b4a3b82,0x3ba33bd5,0x3abd3b08,0x3b0a3b5f,0x3a0d3a69,0x3a2d3aa3,0x393c39a8,0x391639a8,0x385038c9,0x379b3877,0x369937a1,0x34c33637,0x346f3587,0x2ef53288,
0xad972248,0x2d6532a1,0xb487b1f4,0xb13ba91b,0xb77ab608,0xb66bb48d,0xb911b86d,0xb8eab817,0xba31b9a8,0xba50b9a8,0xbb13baaa,0xbb54bae0,0xbbacbb69,0xbbe4bbab,0xbbf8bbdc,0xbbf9bbfe,
0xbbfcbbff,0xbbf5bbc9,0xbbb5bbe3,0xbbe9bc00,0xbb1bbb72,0xbb5cbbb2,0xba35bab1,0xba54bae6,0xb90cb9a8,0xb8e5b9a8,0xb759b862,0xb648b80d,0xb44bb5da,0xb0beb45d,0xac38b160,0x2ec3a57f,
0x29b1abd9,0xb010b414,0x340e30cb,0x30421a48,0x373735ab,0x3625342c,0x39073858,0x38e03802,0x3a3939a8,0x3a5839a8,0x3b243ab8,0x3b633aed,0x3bbd3b7b,0x3bee3bb9,0x3bfe3be9,0x3bef3c00,
0x3bff3bf8,0x3be93baf,0x3bc53bee,0x3bf23c00,0x3b2c3b84,0x3b6a3bc0,0x3a3d3abf,0x3a5c3af3,0x390239a8,0x38db39a8,0x3715384d,0x360237ee,0x33a2357c,0x2f8b33f7,0x25e43036,0xb0bea3db,
0x96482f0e,0x316c34d5,0xb328af40,0xae912852,0xb6f4b54c,0xb5dfb396,0xb8fdb842,0xb8d6b7d8,0xba41b9a8,0xba60b9a8,0xbb35bac6,0xbb71baf9,0xbbccbb8c,0xbbf5bbc6,0xbc00bbf3,0xbbe2bbff,
0xbc00bbed,0xbbdabb91,0xbbd3bbf7,0xbbf8bbfd,0xbb3dbb95,0xbb78bbcb,0xba45bacc,0xba64baff,0xb8f8b9a8,0xb8d1b9a8,0xb6d2b838,0xb5bcb7c2,0xb2adb51d,0xad97b334,0x251bae14,0x32192aac,
0xa94db115,0xb2c6b593,0x32322ce7,0x2c9cac83,0x36af34ed,0x359932d2,0x38f3382d,0x38cc37ac,0x3a4939a8,0x3a6739a8,0x3b453ad3,0x3b7f3b05,0x3bd93b9d,0x3bfb3bd1,0x3bfe3bfa,0x3bd23bfb,
0x3bfc3bdd,0x3bc83b6e,0x3bdf3bfd,0x3bfd3bf8,0x3b4c3ba4,0x3b853bd6,0x3a4d3ad9,0x3a6b3b0b,0x38ee39a8,0x38c739a8,0x368d3822,0x35763796,0x31b634bd,0x2b43326f,0xac062b75,0xb371adb0,
0x340e364e,0x36a43887,0xa94d2edc,0x2d333408,0xb552b20d,0xb432ade2,0xb8c1b780,0xb899b6cc,0xba6fb9a8,0xba8cb9a8,0xbb8bbb11,0xbbb8bb3e,0xbbfebbdb,0xbbf9bbf7,0xbbbdbbf4,0xbb47bbbe,
0xbbb2bb46,0xbb35ba7c,0xbbffbbf0,0xbbf6bbb4,0xbb92bbe0,0xbbbdbbf9,0xba73bb17,0xba90bb43,0xb8bcb9a8,0xb894b9a8,0xb52fb76a,0xb40eb6b5,0xa6adb1aa,0x2e2dad1a,0x34633004,0x36f43451,
0xb4b7b705,0xb742b8d8,0x217fb099,0xaf27b499,0x350b3147,0x33d32c51,0x38b73753,0x388e369e,0x3a7639a8,0x3a9339a8,0x3b983b1d,0x3bc23b49,0x3c003be4,0x3bf33bfb,0x3ba53beb,0x3b213baa,
0x3b983b1a,0x3b0d3a3f,0x3c003be5,0x3bef3b9e,0x3b9e3be8,0x3bc63bfd,0x3a7a3b22,0x3a973b4e,0x38b239a8,0x388939a8,0x34e7373d,0x33893687,0x9cb630e4,0xb0102b11,0xb50bb12e,0xb790b4e1,
0x355e37b7,0x37dd3927,0x251b31c3,0x308d3529,0xb4c3b080,0xb340a97f,0xb8adb726,0xb884b670,0xba7eb9a8,0xba9bb9a8,0xbba3bb28,0xbbcbbb53,0xbc00bbec,0xbbebbbfe,0xbb89bbdf,0xbaf7bb93,
0xbb7abae9,0xbae1b9fe,0xbbffbbd7,0xbbe6bb86,0xbba9bbef,0xbbcfbbff,0xba81bb2e,0xba9ebb58,0xb8a8b9a8,0xb87fb9a8,0xb49fb710,0xb2f7b659,0x2884b01d,0x3109a7da,0x35b13257,0x38153570,
0xb602b832,0xb83ab972,0xaa7ab2ea,0xb185b5b6,0x347b2f72,0x32ad24b6,0x38a336f9,0x387a3642,0x3a8539a8,0x3aa239a8,0x3bae3b33,0x3bd33b5d,0x3bfd3bf2,0x3be13c00,0x3b6a3bd0,0x3acb3b79,
0x3b593ab5,0x3ab339ba,0x3bfc3bc7,0x3bdc3b6b,0x3bb33bf5,0x3bd73c00,0x3a893b39,0x3aa53b62,0x389e39a8,0x387439a8,0x345736e3,0x3263362b,0xac382eaa,0xb2011e48,0xb654b37d,0xb85fb5fd,
0xb99ab997,0xb89fb873,0xb99eb99c,0xb8f5b8ca,0xb9a3b9a0,0xb947b91e,0xb9a7b9a5,0xb995b96e,0xb9abb9a9,0xb9e0b9bb,0xb9b0b9ae,0xba26ba03,0xb9b4b9b2,0xba68ba48,0xb9b9b9b7,0xbaa6ba88,
0xb9d3b9d9,0xba9fbac0,0xb9c6b9cc,0xba59ba7d,0xb9b9b9bf,0xba0eba34,0xb9abb9b2,0xb9bdb9e6,0xb99eb9a5,0xb967b993,0xb991b997,0xb90db93b,0xb983b98a,0xb8aeb8de,0xb975b97c,0xb84cb87e,
0x395e3953,0x385c3824,0x3975396a,0x38c83892,0x398c3981,0x392f38fc,0x39a33997,0x39913961,0x39b939ae,0x39ec39bf,0x39cf39c4,0x3a423a18,0x39e439d9,0x3a913a6a,0x39f939ef,0x3ad93ab6,
0x3a0a3a18,0x3acb3af0,0x39ec39fb,0x3a7b3aa4,0x39cf39de,0x3a223a4f,0x39b039bf,0x39c139f3,0x399139a0,0x395a398e,0x39713981,0x38eb3923,0x39503961,0x387638b1,0x392f3940,0x37f63839,
0xb921b90b,0xb816b7a4,0xb94bb936,0xb89ab859,0xb975b961,0xb917b8d9,0xb99eb98a,0xb98cb953,0xb9c6b9b2,0xb9f9b9c4,0xb9ecb9d9,0xba5dba2c,0xba12b9ff,0xbab7ba8b,0xba36ba24,0xbb07bae1,
0xba3eba53,0xbaf5bb1d,0xba12ba28,0xba9bbaca,0xb9e4b9fb,0xba36ba6a,0xb9b4b9cc,0xb9c6b9ff,0xb983b99c,0xb94bb98a,0xb950b96a,0xb8c8b90b,0xb91cb936,0xb83cb883,0xb8e6b901,0xb750b7e6,
0x38e138c0,0x379e36fc,0x39213901,0x386b381e,0x395e3940,0x38fe38b6,0x399a397c,0x39883944,0x39d339b7,0x3a0539c8,0x3a0a39ef,0x3a773a40,0x3a3e3a24,0x3adc3aab,0x3a703a57,0x3b333b09,
0x3a703a8b,0x3b1c3b47,0x3a363a53,0x3abb3aed,0x39f93a18,0x3a4a3a84,0x39b939d9,0x39ca3a0c,0x39753997,0x393d3985,0x392f3953,0x38a438f2,0x38e6390b,0x38003854,0x389a38c0,0x36a73756,
0xb70db651,0xb4aeb309,0xb83cb7c5,0xb6ebb5d1,0xb8e6b892,0xb880b7fb,0xb983b936,0xb971b8fc,0xba12b9cc,0xba42b9de,0xba91ba53,0xbaefba9d,0xbafebaca,0xbb74bb37,0xbb5abb2e,0xbbcebba6,
0xbb40bb6c,0xbbb2bbd8,0xbad9bb0f,0xbb43bb80,0xba5dba9d,0xbaa6bafa,0xb9cfba18,0xb9e0ba48,0xb92fb981,0xb8f5b96e,0xb880b8d9,0xb7d5b873,0xb788b824,0xb590b6b8,0xb5fab6c3,0xb251b460,
0x367935a2,0x34113197,0x380b374b,0x3684354f,0x38cd386e,0x386637af,0x397e3928,0x396c38ed,0x3a1e39d1,0x3a4e39e2,0x3aa93a66,0x3b043aaf,0x3b1f3ae7,0x3b8c3b4e,0x3b7d3b51,0x3be03bbd,
0x3b613b8d,0x3bc73be8,0x3af53b2e,0x3b5a3b97,0x3a703ab6,0x3ab73b0f,0x39d33a24,0x39e43a53,0x3921397c,0x38e6396a,0x385c38c0,0x37883859,0x370d37e6,0x350e3651,0x3549362e,0x30de3383,
0xb5e2b4f0,0xb2e4b023,0xb7b4b6cf,0xb61db4cc,0xb8b4b849,0xb84cb761,0xb97ab919,0xb967b8de,0xba2ab9d5,0xba59b9e6,0xbac1ba79,0xbb19bac0,0xbb3dbb03,0xbba2bb65,0xbb9cbb70,0xbbefbbd0,
0xbb7fbbaa,0xbbd8bbf4,0xbb10bb4c,0xbb6fbbac,0xba82bacd,0xbac8bb23,0xb9d7ba30,0xb9e8ba5f,0xb912b978,0xb8d7b965,0xb836b8a7,0xb73ab83e,0xb690b783,0xb48ab5e8,0xb496b596,0xaecfb244,
0x3549343b,0x31a42d58,0x37503651,0x35b33447,0x389a3824,0x38313713,0x3975390b,0x396338cf,0x3a3639d9,0x3a6539ea,0x3ad93a8b,0x3b2d3ad0,0x3b5a3b1d,0x3bb53b7a,0x3bb73b8d,0x3bf93be0,
0x3b9a3bc3,0x3be73bfc,0x3b2a3b67,0x3b833bbe,0x3a943ae4,0x3ad93b37,0x39db3a3c,0x39ec3a6a,0x39033973,0x38c83961,0x3811388d,0x36eb3824,0x3611371e,0x3405357e,0x33c034fc,0x2bc03103,
0xb061a8cf,0x25b230ac,0xb549b383,0xb32eae84,0xb816b6c3,0xb750b57e,0xb95eb8c0,0xb94bb883,0xba70b9ef,0xba9bb9ff,0xbb40bae1,0xbb83bb1d,0xbbc7bb8d,0xbbf5bbcc,0xbbffbbed,0xbbeabbff,
0xbbf2bc00,0xbbfebbe3,0xbb96bbcf,0xbbd2bbf9,0xbae9bb49,0xbb25bb8b,0xb9f1ba75,0xba01baa1,0xb8b9b95c,0xb87bb949,0xb69bb809,0xb555b734,0xb2fdb514,0xad71b2bf,0xa376af7e,0x31662966,
0x2e39a052,0xabf2b21f,0x34de3276,0x32512c5e,0x37f63673,0x3718352c,0x395a38b1,0x39473873,0x3a7b39f3,0x3aa63a03,0x3b523af0,0x3b923b2c,0x3bd63b9f,0x3bfb3bd8,0x3c003bf6,0x3bda3bfc,
0x3bfa3bff,0x3bf93bd1,0x3ba73bdd,0x3bdd3bfd,0x3af83b5b,0x3b333b99,0x39f53a80,0x3a053aab,0x38a93957,0x386b3944,0x364b37db,0x350236fc,0x31ee34a8,0x2a9331e2,0xa8062cf4,0xb2d8ad3f,
0xab5c2af8,0x2e843390,0xb472b166,0xb172a86b,0xb7bfb622,0xb6e0b4d8,0xb955b8a2,0xb942b863,0xba86b9f7,0xbab0ba08,0xbb64bb00,0xbba0bb39,0xbbe3bbaf,0xbbffbbe2,0xbbfdbbfd,0xbbc6bbf5,
0xbbffbbfa,0xbbf1bbba,0xbbb7bbe8,0xbbe7bc00,0xbb07bb6c,0xbb40bba6,0xb9f9ba8b,0xba0abab6,0xb89ab953,0xb85cb940,0xb5fab7a4,0xb4aeb6c3,0xb0deb43b,0xa484b103,0x2cf4a8cf,0x34232fc9,
0x2484ae6b,0xb086b47e,0x34053055,0x30931248,0x378835d1,0x36a73484,0x39503892,0x393d3854,0x3a9139fb,0x3abb3a0c,0x3b743b0f,0x3bad3b47,0x3bed3bbe,0x3c003beb,0x3bf63c00,0x3bae3beb,
0x3c003bf0,0x3be53ba0,0x3bc53bf2,0x3bef3c00,0x3b163b7c,0x3b4d3bb3,0x39fd3a96,0x3a0e3ac0,0x388b394e,0x384c393b,0x35a8376c,0x345a368a,0x2f97339c,0xa4203023,0xafe298b6,0xb4d8b128,
0x31c93531,0x355b37e0,0xaf652839,0x9d7f315a,0xb66db42f,0xb584b1b0,0xb939b844,0xb925b803,0xbac5ba10,0xbaecba20,0xbbb9bb53,0xbbdfbb82,0xbbffbbf2,0xbbe3bc00,0xbb91bbde,0xbaf7bb8a,
0xbbd6bb81,0xbb7cbadf,0xbbf5bbfd,0xbc00bbdd,0xbb5abbbe,0xbb88bbe3,0xba12baca,0xba22baf0,0xb83cb936,0xb7f6b923,0xb405b651,0xb15ab567,0x2a61ae84,0x31e22052,0x358a3269,0x381935a8,
0xb309b5e2,0xb5f4b841,0x2da3ac44,0xa5b2b269,0x363433b4,0x35493103,0x39343834,0x392137e6,0x3acf3a14,0x3af53a24,0x3bc43b60,0x3be73b8d,0x3bfb3bf8,0x3bd63bff,0x3b703bce,0x3ac63b6d,
0x3bc53b5f,0x3b5d3aad,0x3bfa3bf9,0x3bff3bcf,0x3b663bc9,0x3b923bea,0x3a163ad4,0x3a263afa,0x382c3931,0x37d5391e,0x335f3617,0x30ac352c,0xad582cc2,0xb2f0a89d,0xb63ab3a8,0xb869b63f,
0x34233690,0x368a3890,0xabc02e6b,0x2a613377,0xb5fab309,0xb50eb055,0xb92fb824,0xb91cb7c5,0xbad9ba18,0xbafeba28,0xbbcebb6c,0xbbedbb97,0xbbf6bbfc,0xbbc7bbfd,0xbb4cbbba,0xba93bb4d,
0xbbafbb38,0xbb3cba77,0xbbfebbf2,0xbbfcbbbf,0xbb72bbd3,0xbb9cbbf0,0xba1abadd,0xba2abb03,0xb81cb92d,0xb7b4b919,0xb2b3b5dc,0xaffbb4f0,0x2f7ea9fd,0x33fd2c12,0x36e53472,0x38b636d4,
0xb4c0b73a,0xb71eb8dc,0x2839b048,0xacf4b441,0x35bf325d,0x34d22f4c,0x392a3813,0x391737a4,0x3ae23a1c,0x3b073a2c,0x3bd73b77,0x3bf33ba1,0x3bee3bff,0x3bb63bfa,0x3b233ba4,0x3a5b3b2a,
0x3b973b0d,0x3b183a3e,0x3c003be9,0x3bf73bad,0x3b7d3bdb,0x3ba63bf5,0x3a1e3ae7,0x3a2e3b0c,0x380b3928,0x37933914,0x320735a2,0x2e9d34b4,0xb0d124e9,0xb484add5,0xb78eb50e,0xb901b767,
0xb97239ba,0x39dc3996,0xb8323ab5,0x3ad0385d,0x3927b9fe,0xba1fb94d,0x37b7bae9,0xbb02b807,0xb8d83a3f,0x3a5e3900,0xb7053b1a,0x3b30375e,0x3887ba7c,0xba99b8b0,0x364ebb46,0xbb5ab6aa,
0xb90039dc,0x3a3f3972,0xad7e3be6,0x3bf83115,0x3807ba99,0xbae9b887,0xabd9bc00,0xbbfca248,0xb5f13b30,0x3b6e3705,0x32a13bed,0x3bd4b04e,0x3365bba0,0xbbc9b4d5,0xb593bbaf,0xbb803475,
0xb88739fe,0x3a99394d,0x35f13bbc,0x3b6eb414,0x3593bb1a,0xbb80b75e,0xb8b0bb02,0xba7c37b7,0xaf0e3bc9,0x3bf43365,0x3a1f39dc,0x3927b972,0xb04ebc00,0xbbed2248,0xbb30b85d,0xb7053ab5,
0xb8073a1f,0x3ae93927,0x39fe3a3f,0x394db900,0x31dbbb80,0xbbddb593,0xbb6eb832,0xb5f13ad0,0x31153c00,0x3be62248,0x3bff32a1,0x28b6bbd4,0xb7b7bb91,0xbb023534,0xbba0304e,0x34d53bed,
0xb7053a3f,0x3b303900,0x3bbc375e,0x3414bb1a,0x2248bbc9,0xbc00b365,0xbbdda8b6,0x31db3bff,0x36aa3bd4,0x3b46b2a1,0x3a7cb64e,0xb8b0bb5a,0xba1fba5e,0xb92738d8,0xb7b739fe,0x3b02394d,
0xb5f13a5e,0x3b6e38d8,0x3bd42bd9,0xb2a1bbfc,0xb115bbf4,0xbbe6af0e,0xb9dc375e,0x39723b1a,0x39273b46,0x3a1fb6aa,0x3475bad0,0xbbafb832,0xbb91b887,0xb5343a99,0x34143c00,0x3bbc2248,
0xb4d53a7c,0x3ba038b0,0x3a3fb593,0xb900bb80,0xb534bc00,0xbb912248,0xb4143ab5,0x3bbc385d,0x3a993a5e,0x3887b8d8,0xb5f1bbfc,0xbb6e2bd9,0xbbffb475,0x28b63baf,0x3ad03a1f,0x3832b927,
0xb3653a99,0x3bc93887,0x36aab996,0xbb46b9ba,0xb7b7bbed,0xbb02304e,0x34d53bfc,0x3ba02bd9,0x3b913927,0x3534ba1f,0xbae9ba3f,0xb8073900,0xbb5a28b6,0x364e3bff,0x3bd43115,0xb2a1bbe6,
0xb1153ab5,0x3be6385d,0xa8b6bb6e,0xbbffb5f1,0xb900bbbc,0xba3f3414,0x3a1f3b30,0x3927b705,0x3bfc375e,0x2bd9bb1a,0xbbedb475,0x304e3baf,0xb9ba3593,0x39963b80,0x3887b832,0xba99bad0,
0xad7e3ad0,0x3bf83832,0xb7b7bbff,0xbb0228b6,0xb9febb6e,0xb94d35f1,0x3bed3887,0x304eba99,0x3bd43414,0xb2a1bbbc,0xb9963534,0x39ba3b91,0xb6aa3900,0x3b463a3f,0xb115bba0,0xbbe6b4d5,
0xa2483ae9,0x3c003807,0xba99bb30,0xb8873705,0xbad0bb02,0xb83237b7,0x3b462d7e,0xb6aabbf8,0x3b1a28b6,0xb75ebbff,0xaf0e3a7c,0x3bf438b0,0xabd93ab5,0x3bfc385d,0xba5ebb5a,0xb8d8364e,
0x2bd93b02,0x3bfc37b7,0xbbedb927,0xb04e3a1f,0xbb6eba7c,0xb5f138b0,0x385db6aa,0xbab5bb46,0x39dcb1db,0xb972bbdd,0x38323c00,0x3ad02248,0x34d53bbc,0x3ba03414,0xbbf4b705,0x2f0e3b30,
0x304e3b1a,0x3bed375e,0xbb91b475,0x35343baf,0xbbd4b9dc,0xb2a13972,0x2248ba7c,0xbc00b8b0,0x3832b64e,0xbad0bb5a,0x3b803a99,0x3593b887,0x39003bfc,0x3a3fabd9,0xb9273414,0x3a1f3bbc,
0x32a13b30,0x3bd43705,0xb996304e,0x39ba3bed,0xbbffb927,0xa8b63a1f,0xb832bbf4,0xbad0af0e,0x3475b8b0,0xbbafba7c,0x3ba03593,0xb4d5bb80,0x3ae93b6e,0x3807b5f1,0x2bd93a99,0x3bfc3887,
0x34753b46,0x3baf36aa,0xb4d53832,0x3ba03ad0,0xbbedb85d,0x304e3ab5,0xbb30bb5a,0xb705364e,0x2248b9fe,0xbc00b94d,0x3887b414,0xba99bbbc,0x3be63a1f,0x3115b927,0x39dc3bf4,0x3972af0e,
0x35933b5a,0x3b80364e,0x31153a99,0x3be63887,0xbba0b705,0x34d53b30,0xbbf4b8d8,0x2f0e3a5e,0xb414bb02,0xbbbcb7b7,0xabd9ba1f,0xbbfcb927,0x3bd43832,0xb2a1bad0,0x3c003972,0xa248b9dc,
0x36aa3b6e,0x3b4635f1,0x38b03bdd,0x3a7c31db,0xbb1ab534,0x375e3b91,0xba3fb04e,0x39003bed,0xb807bbaf,0xbae9b475,0xb94dbbf8,0xb9fead7e,0x3ab53365,0xb85dbbc9,0x39ba28b6,0xb996bbff,
0x37b73b80,0x3b023593,0x3b1a3bc9,0x375eb365,0xba5eb2a1,0x38d83bd4,0xb53435f1,0x3b913b6e,0xb9babbfc,0xb996abd9,0xbbddbae9,0xb1db3807,0x38b0ad7e,0xba7cbbf8,0x28b6b900,0xbbffba3f,
0x385d3b91,0x3ab53534,0x3c003a5e,0x2248b8d8,0xb972ad7e,0x39dc3bf8,0x33653a3f,0x3bc93900,0xbb02bbe6,0xb7b73115,0xbb1ab6aa,0x375e3b46,0x3414b64e,0xbbbcbb5a,0xb94dbbdd,0xb9feb1db,
0x38d83ba0,0x3a5e34d5,0x3b3037b7,0xb705bb02,0xb85d28b6,0x3ab53bff,0x39ba3be6,0x39963115,0xbbc9bb6e,0xb36535f1,0xb6aa31db,0x3b463bdd,0xaf0eb94d,0xbbf4b9fe,0xbbf8bae9,0xad7e3807,
0x394d3baf,0x39fe3475,0x38d82d7e,0xba5ebbf8,0xb64e3115,0x3b5a3be6,0x3bd43b80,0x32a1b593,0xbbffba99,0x28b63887,0x336539ba,0x3bc93996,0xb75ebae9,0xbb1ab807,0xba3fb534,0x39003b91,
0x39ba3bbc,0x39963414,0x31dbb534,0xbbddbb91,0xb3653475,0x3bc93baf,0x3b803927,0xb593ba1f,0xbba0b972,0x34d539dc,0x3a3f3be6,0x39003115,0xb9febbd4,0xb94db2a1,0xb04e35f1,0x3bed3b6e,
0x3a1f3bc9,0x39273365,0xb475b972,0xbbafb9dc,0xabd9364e,0x3bfc3b5a,0x38d831db,0xba5ebbdd,0xbab5b807,0x385d3ae9,0x3c003b30,0x2248b705,0xbb80bbf4,0xb5932f0e,0x38b03b1a,0x3a7c375e,
0x3a7c3bd4,0x38b032a1,0xb972bb5a,0xb9dcb64e,0x2f0e3807,0x3bf43ae9,0x2d7eb534,0xbbf8bb91,0xb94db4d5,0x39fe3ba0,0x3a5e37b7,0xb8d8bb02,0xbc00bb46,0x224836aa,0x3bdd3bc9,0x31dbb365,
0x3ad03bdd,0x383231db,0xbb80bc00,0xb5932248,0x347538d8,0x3baf3a5e,0xb75eb9fe,0xbb1ab94d,0xb705ad7e,0x3b303bf8,0x3414af0e,0xbbbcbbf4,0xbb6eb9dc,0x35f13972,0x3ab538b0,0xb85dba7c,
0x3b1a3be6,0x375e3115,0xbbf4bb46,0x2f0e36aa,0x37053996,0x3b3039ba,0xbae9bbd4,0xb807b2a1,0xb1db304e,0x3bdd3bed,0xb64eb94d,0xbb5ab9fe,0xb9dcb7b7,0x39723b02,0x3365ad7e,0xbbc9bbf8,
0x3b5a3bed,0x364e304e,0xbab5b94d,0x385d39fe,0x38b03a3f,0x3a7c3900,0xbbffbba0,0x28b634d5,0x2d7e3593,0x3bf83b80,0xbb02bbc9,0xb7b7b365,0xb705b1db,0x3b303bdd,0xb807b9ba,0xbae9b996,
0x3b913bf4,0x35342f0e,0xb807b4d5,0x3ae93ba0,0x39ba3ad0,0x39963832,0xba99b972,0x388739dc,0x3593385d,0x3b803ab5,0xbbe6bb6e,0x311535f1,0xad7e304e,0x3bf83bed,0xbbafbbfc,0xb475abd9,
0x3bbc3bf8,0x34142d7e,0xabd92f0e,0x3bfc3bf4,0x3a993b46,0x388736aa,0xb64eb365,0x3b5a3bc9,0x38b039ba,0x3a7c3996,0xb972b85d,0x39dc3ab5,0x34753705,0x3baf3b30,0xbb1aba5e,0x375e38d8,
0x3bdd3bfc,0x31db2bd9,0x364e3807,0x3b5a3ae9,0x3b463ba0,0x36aa34d5,0x31153475,0x3be63baf,0x3a3f3ad0,0x39003832,0xad7e28b6,0x3bf83bff,0x38d83996,0x3a5e39ba,0xb534b2a1,0x3b913bd4,
0x3bf43bff,0x2f0e28b6,0x3a1f3a7c,0x392738b0,0x3bbc3bdd,0x341431db,0x394d39ba,0x39fe3996,0x3b5a3b91,0x364e3534,0x385d38d8,0x3ab53a5e,0x3ad03b1a,0x3832375e,0x36aa37b7,0x3b463b02,
0x3bff3c00,0x28b62248,0x3bc93bd4,0x336532a1,0x3bf83bfc,0x2d7e2bd9,0x3baf3bbc,0x34753414,0x3bed3bf4,0x304e2f0e,0x3b913ba0,0x353434d5,0x3bdd3be6,0x31db3115,0x3b6e3b80,0x35f13593,
0xb5933b6e,0x3b8035f1,0xb1153bdd,0x3be631db,0x34d5bb91,0xbba0b534,0x2f0ebbed,0xbbf4b04e,0xb4143baf,0x3bbc3475,0xabd93bf8,0x3bfc2d7e,0x32a1bbc9,0xbbd4b365,0x2248bbff,0xbc00a8b6,
0x37b73b46,0x3b02b6aa,0x3b1a3832,0x375ebad0,0xb8d8bab5,0xba5e385d,0xbb91b64e,0xb5343b5a,0x39ba39fe,0x3996b94d,0x3bdd3414,0x31dbbbbc,0xba7cb927,0xb8b03a1f,0xbbffaf0e,0xa8b63bf4,
0x3bd43534,0x32a1bb91,0x39bab8d8,0xb996ba5e,0xbbffad7e,0x28b63bf8,0xb8323a3f,0x3ad03900,0x3bafb115,0xb475bbe6,0x34d5bb46,0xbba0b6aa,0xbae9364e,0x38073b5a,0xabd93bdd,0x3bfc31db,
0x3a5eb75e,0xb8d8bb1a,0xb705bbaf,0xbb303475,0xb85d39dc,0x3ab53972,0x39ba3a7c,0x3996b8b0,0x3365bb5a,0xbbc9b64e,0xbb46b887,0xb6aa3a99,0x2f0e3bfc,0x3bf42bd9,0x3bf83414,0x2d7ebbbc,
0x2bd9bbaf,0xbbfcb475,0xbbedad7e,0x304e3bf8,0x35f13be6,0x3b6eb115,0x3ab5b593,0xb85dbb80,0xb9dcba99,0xb9723887,0xb83239ba,0x3ad03996,0x3ba03807,0x34d5bae9,0x2f0ebb91,0xbbf4b534,
0xb9babae9,0xb9963807,0xb1db3b30,0x3bdd3705,0x3bc937b7,0x3365bb02,0xb593bbf8,0xbb802d7e,0xbba028b6,0x34d53bff,0x3a3f3a7c,0x3900b8b0,0x394db85d,0xb9febab5,0xbbedb64e,0xb04e3b5a,
0xbbf8b365,0x2d7e3bc9,0x3b0239dc,0x37b7b972,0x39feb64e,0xb94dbb5a,0xbbedb1db,0x304e3bdd,0xb2a13ae9,0x3bd43807,0x39bab705,0xb996bb30,0xb6aabbf4,0xbb462f0e,0xb1153b1a,0x3be6375e,
0xb8b0385d,0x3a7c3ab5,0x39dcb5f1,0xb972bb6e,0xaf0ebbbc,0xbbf4b414,0xad7e3b30,0x3bf83705,0x39fe3b1a,0x394db75e,0xb8d8bbaf,0xba5e3475,0xbc00b593,0x22483b80,0x3bdd3832,0x31dbbad0,
0x33653bdd,0x3bc931db,0xb6aabc00,0xbb462248,0xbb02ba5e,0xb7b738d8,0x3ba0394d,0x34d5b9fe,0x3b912d7e,0xb534bbf8,0xbae92f0e,0x38073bf4,0xb64e3972,0x3b5a39dc,0x32a1ba7c,0xbbd4b8b0,
0x3b1a3a7c,0x375eb8b0,0xbbf4b593,0x2f0e3b80,0xbb30a248,0x37053c00,0x3807b85d,0xbae9bab5,0x31dbba5e,0xbbddb8d8,0x364e3bfc,0x3b5a2bd9,0x39723baf,0x39dcb475,0xbbc9b927,0xb3653a1f,
0x3b6e304e,0xb5f1bbed,0xb2a139fe,0x3bd4394d,0xb1153a3f,0x3be63900,0xb9dcbba0,0xb97234d5,0xba1fbb80,0xb9273593,0x3baf3365,0xb475bbc9,0x3b9131db,0xb534bbdd,0xb41439ba,0x3bbc3996,
0x3534b900,0xbb91ba3f,0x3ae93b1a,0x3807b75e,0x39ba3bc9,0x3996b365,0xba9928b6,0x38873bff,0xbb80b2a1,0x35933bd4,0xb115bb5a,0xbbe6b64e,0x2d7eba5e,0xbbf8b8d8,0x3baf39fe,0x3475b94d,
0xb807bbf8,0xbae9ad7e,0x39feaf0e,0xb94dbbf4,0x3bdd36aa,0xb1dbbb46,0x35f13bc9,0x3b6e3365,0xb11539ba,0x3be63996,0xbbffb85d,0x28b63ab5,0xbb02bb30,0xb7b73705,0x34d5b8d8,0xbba0ba5e,
0xbbddb9fe,0xb1db394d,0xb64ebbbc,0xbb5ab414,0x36aab75e,0xbb46bb1a,0x3be637b7,0xb115bb02,0x3a3f3bc9,0x3900b365,0xad7e39dc,0x3bf83972,0xba5ea248,0x38d83c00,0xbb91bab5,0xb534385d,
0xba3fa8b6,0x39003bff,0xbbf8b8b0,0x2d7e3a7c,0xb807bbdd,0xbae9b1db,0x2bd9b9ba,0xbbfcb996,0x3b6e3534,0xb5f1bb91,0x3bd43a5e,0x32a1b8d8,0x33653b1a,0x3bc9375e,0xb59337b7,0x3b803b02,
0xa8b63996,0x3bff39ba,0xb365385d,0x3bc93ab5,0xbbf8b9fe,0xad7e394d,0xbbafbae9,0xb4753807,0x304eb900,0xbbedba3f,0x3534b75e,0xbb91bb1a,0x3bdd3a7c,0x31dbb8b0,0x3b6e3b46,0x35f1b6aa,
0x39dc3c00,0x3972a248,0x3ad03bd4,0x3832b2a1,0xb9272bd9,0x3a1f3bfc,0xb7b73414,0x3b023bbc,0xba5ebbf4,0xb8d82f0e,0xbb30bba0,0xb70534d5,0x3887b115,0xba99bbe6,0x364eb593,0xbb5abb80,
0x3bf43972,0xaf0eb9dc,0x3a1f3115,0xb927bbe6,0x34143a99,0x3bbc3887,0x39fe3c00,0x394d2248,0xbb5ab705,0x364e3b30,0xb85d304e,0x3ab53bed,0xb832bba0,0xbad0b4d5,0xbb46bbaf,0xb6aa3475,
0x3887abd9,0xba99bbfc,0xb5f1bae9,0xbb6eb807,0x3b803ba0,0x3593b4d5,0x3a7c3475,0xb8b0bbaf,0xaf0e3832,0x3bf43ad0,0x3a1f3bff,0x392728b6,0xbbedb996,0x304e39ba,0xb70532a1,0x3b303bd4,
0xb414ba1f,0xbbbcb927,0xbbfcba3f,0x2bd93900,0x3a993593,0xb887bb80,0xb64ebad0,0xbb5ab832,0x3a7c3c00,0x38b02248,0x39dc32a1,0xb972bbd4,0xb4753534,0x3baf3b91,0x3b1a3bed,0x375eb04e,
0xbb30bbf4,0xb7052f0e,0xb41434d5,0x3bbc3ba0,0x2248b832,0xbc00bad0,0xbbddb9dc,0x31db3972,0x3b46385d,0xb6aabab5,0xb8b0bb6e,0xba7cb5f1,0x3a1f3bed,0x3927304e,0x37b7abd9,0xbb02bbfc,
0xbb5ab8d8,0x364e3a5e,0x3ab53bfc,0x385d2bd9,0xba7cbbf4,0xb8b0af0e,0xa8b6375e,0x3bff3b1a,0x2d7eb6aa,0xbbf8bb46,0xbb02b832,0x37b73ad0,0x3b303887,0xb705ba99,0xbae9bc00,0xb807a248,
0xb4d53115,0x3ba03be6,0x3a3f36aa,0xb900bb46,0xbb91b996,0x353439ba,0x3bbc3bd4,0x3414b2a1,0xba99bbed,0xb887b04e,0x35f139fe,0x3b6e394d,0xa8b6b7b7,0xbbffbb02,0xb832ad7e,0x3ad03bf8,
0x38323a99,0x3ad03887,0xb593b996,0xbb80b9ba,0xb475304e,0x3baf3bed,0x375e2bd9,0xbb1abbfc,0xbb30b927,0x37053a1f,0x3bbc3a3f,0xb414b900,0xbb6ebbff,0xb5f128b6,0x3ab53be6,0x385d3115,
0x3be63bd4,0x3115b2a1,0xbbffbb5a,0x28b6364e,0x39003ae9,0x3a3f3807,0xba1fbb91,0xb927b534,0xabd934d5,0x3bfc3ba0,0xb04eb7b7,0xbbedbb02,0xb9bab6aa,0x39963b46,0x38873365,0xba99bbc9,
0x3a1f3832,0xb927bad0,0xb47528b6,0x3baf3bff,0x3bfc3b6e,0xabd9b5f1,0xba5eb887,0x38d83a99,0x3ab53bbc,0x385d3414,0xbc00bb91,0x22483534,0x35933900,0x3b803a3f,0xba7cbba0,0xb8b0b4d5,
0x2248b414,0xbc00bbbc,0x3a993b91,0x38873534,0x38323475,0xbad0bbaf,0x36aa3927,0x3b463a1f,0x3b1a39dc,0xb75eb972,0xaf0e3115,0x3bf43be6,0x3bfc3bd4,0x2bd9b2a1,0xb8d8b5f1,0x3a5e3b6e,
0xb9febb02,0xb94db7b7,0x3a5e3927,0xb8d8ba1f,0xb64eb8b0,0xbb5aba7c,0x3bd43b46,0xb2a1b6aa,0x28b6b1db,0xbbffbbdd,0x3bc93c00,0x33652248,0x375e3414,0xbb1abbbc,0x3a3f3b30,0x39003705,
0xbbedbba0,0x304e34d5,0xb534b7b7,0xbb91bb02,0xbbd4bbff,0xb2a1a8b6,0x2248b115,0xbc00bbe6,0xbad0bb6e,0xb832b5f1,0x359331db,0xbb80bbdd,0xb900b9fe,0xba3fb94d,0x39273807,0xba1fbae9,
0xb85db705,0x3ab53b30,0xbc00bbed,0x2248304e,0xb9dcb927,0x39723a1f,0xbbc9bbf4,0xb365af0e,0xbb02ba7c,0x37b738b0,0xbb1abb80,0xb75eb593,0xbbbcbb6e,0x341435f1,0xb9feba99,0xb94db887,
0x34753593,0x3baf3b80,0xb4d5b365,0x3ba03bc9,0x304e32a1,0x3bed3bd4,0xb705b5f1,0x3b303b6e,0xa2482bd9,0x3c003bfc,0xb887b807,0x3a993ae9,0xb115ad7e,0x3be63bf8,0xb972b900,0x39dc3a3f,
0x3b463b5a,0x36aa364e,0x3a7c3a99,0x38b03887,0x3b1a3b30,0x375e3705,0x3a3f3a5e,0x390038d8,0x3ae93b02,0x380737b7,0x39fe3a1f,0x394d3927,0x3ab53ad0,0x385d3832,0x39ba39dc,0x39963972,
0x28b63c00,0x3bffa248,0x33653bd4,0x3bc9b2a1,0xad7ebbfc,0xbbf82bd9,0xb475bbbc,0xbbaf3414,0x304e3bf4,0x3bedaf0e,0x35343ba0,0x3b91b4d5,0xb1dbbbe6,0xbbdd3115,0xb5f1bb80,0xbb6e3593,
0x3bf4a8b6,0xaf0ebbff,0x3a1fb8b0,0xb927ba7c,0xbbbc31db,0x34143bdd,0xb94d3996,0x39fe39ba,0x3b5ab534,0xb64ebb91,0x385dba5e,0xbab5b8d8,0xbad0375e,0x38323b1a,0xb6aa3b02,0x3b4637b7,
0xb1dbbbfc,0xbbdd2bd9,0xbb5ab807,0xb64e3ae9,0x36aa3ba0,0x3b46b4d5,0x3be63475,0x3115bbaf,0xb900bad0,0xba3f3832,0xbbf8a8b6,0x2d7e3bff,0x3a5e3996,0x38d8b9ba,0x3b91b2a1,0xb534bbd4,
0xbbbc2d7e,0x34143bf8,0x2bd93bf4,0x3bfc2f0e,0x3a99b6aa,0xb887bb46,0xb64ebbc9,0xbb5a3365,0xb8b03996,0x3a7c39ba,0x39723ab5,0x39dcb85d,0x3475bb30,0xbbafb705,0xbb1ab8d8,0xb75e3a5e,
0x35343bf4,0x3b91af0e,0x3ae9b4d5,0xb807bba0,0xb996bad0,0xb9ba3832,0xb8873972,0x3a9939dc,0x3b80385d,0x3593bab5,0x3115bb6e,0xbbe6b5f1,0xbbf8b04e,0x2d7e3bed,0x34753bfc,0x3bafabd9,
0x3b5ab04e,0xb64ebbed,0xbab5b9fe,0xb85d394d,0xb8b03900,0x3a7c3a3f,0x3bff34d5,0x28b6bba0,0x2d7ebb80,0xbbf8b593,0xbb023365,0x37b73bc9,0x37053bdd,0x3b30b1db,0x3807b996,0xbae9b9ba,
0xb75ebbe6,0xbb1a3115,0xaf0e3b46,0x3bf436aa,0x3b303996,0x3705b9ba,0xb807bbd4,0xbae932a1,0xbbddb04e,0x31db3bed,0x3b5a394d,0x364eb9fe,0x3972b7b7,0xb9dcbb02,0xbbc9ad7e,0x33653bf8,
0xbad031db,0x38323bdd,0x3b802248,0xb593bc00,0x3475ba5e,0xbbafb8d8,0xb75e394d,0x3b1a39fe,0x37053bf8,0x3b30ad7e,0xb414bbf4,0xbbbcaf0e,0xbb6eb972,0xb5f139dc,0x3ab53a7c,0x385db8b0,
0x38b03bd4,0x3a7cb2a1,0xb9dcbb5a,0xb972364e,0xbbf4b807,0xaf0e3ae9,0x3bf83534,0xad7ebb91,0x39feb4d5,0xb94dbba0,0xb8d837b7,0x3a5e3b02,0xa2483b46,0x3c0036aa,0xb1dbbbc9,0xbbddb365,
0x3a1fb365,0xb927bbc9,0xb47539dc,0x3baf3972,0x2bd93b5a,0x3bfc364e,0xb8d8bbdd,0xba5e31db,0xbab5bae9,0xb85d3807,0x3c003705,0xa248bb30,0x3b802f0e,0xb593bbf4,0xb8b0375e,0x3a7c3b1a,
0xb996bbbc,0xb9ba3414,0x3bdd3534,0xb1dbbb91,0x3bc93475,0xb365bbaf,0xb5933927,0x3b803a1f,0xb4d53972,0x3ba039dc,0xb900bbe6,0xba3f3115,0xb94dbbd4,0xb9fe32a1,0x3bed35f1,0xb04ebb6e,
0xb94d3475,0x39fe3baf,0xb8d8bbf8,0xba5e2d7e,0xb64ebbe6,0xbb5ab115,0x3bd43593,0xb2a1bb80,0x3bff3887,0x28b6ba99,0xb3653996,0x3bc939ba,0xb75e3807,0x3b1a3ae9,0xba3fbb91,0xb9003534,
0x3a5e3ba0,0x38d8b4d5,0xb70537b7,0x3b303b02,0xbab5a8b6,0x385d3bff,0xb996bbe6,0xb9ba3115,0xb365bb6e,0xbbc9b5f1,0x3b4631db,0xb6aabbdd,0x3bf4394d,0x2f0eb9fe,0x2d7e3ae9,0x3bf83807,
0x385db534,0xbab5bb91,0x3c0038d8,0xa248ba5e,0x39723bf8,0x39dcad7e,0xb3653900,0x3bc93a3f,0xbb02b115,0x37b73be6,0xbb1abb46,0xb75e36aa,0xb414bb5a,0xbbbcb64e,0x394db1db,0xb9febbdd,
0xbb02bb80,0xb7b73593,0xb75ebbc9,0xbb1ab365,0x38d8b2a1,0xba5ebbd4,0x3b9135f1,0xb534bb6e,0x39963bfc,0x39baabd9,0x31db3ae9,0x3bdd3807,0xba7cad7e,0x38b03bf8,0xbbffb900,0x28b63a3f,
0xb6aa35f1,0x3b463b6e,0xb8b031db,0x3a7c3bdd,0xbb1abb91,0xb75e3534,0xba3fbbed,0xb900304e,0x3807b475,0xbae9bbaf,0x394dad7e,0xb9febbf8,0x3ab53bc9,0x385db365,0x39ba3bff,0x3996a8b6,
0x3b803b5a,0x3593b64e,0x3be63a99,0x3115b887,0xb4d53705,0x3ba03b30,0xaf0e38d8,0x3bf43a5e,0xbbbcbb02,0xb41437b7,0xbbfcba1f,0xabd93927,0x32a1b832,0xbbd4bad0,0x2248b972,0xbc00b9dc,
0x3475b6aa,0xbbafbb46,0xb4d5bad0,0xbba0b832,0x3bed3ab5,0x304eb85d,0x3b30364e,0xb705bb5a,0x2248394d,0x3c0039fe,0x38873bbc,0x3a993414,0xbbe6b927,0x31153a1f,0xb9dcaf0e,0x39723bf4,
0xbbd4bb30,0xb2a13705,0xb9bab04e,0x39963bed,0xa8b6b927,0xbbffba1f,0xbad0bbf4,0xb8322f0e,0x3baf38b0,0xb475ba7c,0x34d5b593,0xbba0bb80,0x38073b6e,0x3ae935f1,0x3bfc3a99,0x2bd9b887,
0xb04e375e,0x3bed3b1a,0x3b913baf,0x3534b475,0xbbd4b972,0x32a139dc,0x224838b0,0x3c003a7c,0xb832bb5a,0xbad0b64e,0xbb80b887,0x35933a99,0x39002bd9,0xba3fbbfc,0xb927bbbc,0xba1fb414,
0x3bfc3b02,0x2bd9b7b7,0xb04eb927,0xbbedba1f,0x35f13a7c,0x3b6e38b0,0x3ab536aa,0xb85dbb46,0xb972b1db,0x39dc3bdd,0x3ad03c00,0x3832a248,0xbba0bbbc,0xb4d53414,0xaf0e3705,0x3bf43b30,
0xa248b807,0xbc00bae9,0xba99b705,0x38873b30,0x3ad037b7,0xb832bb02,0xbb46bbf8,0xb6aa2d7e,0x3b1a3bff,0x375ea8b6,0xaf0eb8b0,0xbbf4ba7c,0x2bd9385d,0x3bfc3ab5,0x3a5e364e,0xb8d8bb5a,
0xbbf8bad0,0x2d7e3832,0x3b023bff,0x37b728b6,0xb94dbb6e,0xb9feb5f1,0x304e3887,0x3bed3a99,0x32a1b414,0xbbd4bbbc,0xb9bab534,0x39963b91,0x3b463900,0xb6aaba3f,0xbbe6bba0,0xb11534d5,
0x3115385d,0x3be63ab5,0x28b6b5f1,0xbbffbb6e,0xb900b414,0x3a3f3bbc,0x3a1f3705,0xb927bb30,0xbbfcbb1a,0x2bd9375e,0x3bed3baf,0x304eb475,0xb9babb80,0xb996b593,0x38873ad0,0x3a993832,
0x3bc93a99,0xb365b887,0xbb46b996,0x36aa39ba,0x3b023bed,0x37b7304e,0xbba0bbfc,0xb4d52bd9,0x35343927,0x3b913a1f,0xb807ba3f,0xbae9b900,0xb64ea8b6,0x3b5a3bff,0x32a1b115,0xbbd4bbe6,
0xb4d5b8b0,0xbba0ba7c,0x3a3f3b80,0x39003593,0x35342248,0xbb91bc00,0x3414385d,0x3bbc3ab5,0x3a9938d8,0xb887ba5e,0xb5f1abd9,0x3b6e3bfc,0x3bff3baf,0x28b6b475,0xbad0b927,0x38323a1f,
0xbb6eba5e,0x35f138d8,0x32a1abd9,0xbbd4bbfc,0xbbe6bbf4,0xb1152f0e,0x3972375e,0xb9dcbb1a,0xba1fbb46,0xb927b6aa,0x3baf3ad0,0xb475b832,0xb534b887,0xbb91ba99,0x3bbc3c00,0x3414a248,
0x37053900,0x3b303a3f,0xbbbcbb1a,0x3414375e,0x22483365,0x3c003bc9,0xbbddbbff,0xb1db28b6,0xb6aab2a1,0x3b463bd4,0xba7cbb5a,0xb8b0b64e,0xba1fb8d8,0x39273a5e,0xb7b7b94d,0xbb02b9fe,
0x3ae93a1f,0xb807b927,0x394d3a3f,0x39fe3900,0x3bdd3b80,0xb1dbb593,0x35f13832,0x3b6e3ad0,0x3be63c00,0x3115a248,0x28b632a1,0x3bff3bd4,0x3b023b91,0x37b73534,0xb4d5b04e,0x3ba03bed,
0xb887b94d,0xba99b9fe,0x35f13414,0xbb6ebbbc,0xb593b75e,0xbb80bb1a,0x38b037b7,0xba7cbb02,0xaf0eb365,0xbbf4bbc9,0x3a1f3972,0xb927b9dc,0x304e2248,0xbbedbc00,0x3b303ab5,0xb705b85d,
0xba3fb9dc,0x39003972,0xbbf8bbe6,0x2d7e3115,0xbae9ba99,0x38073887,0xbbfcbc00,0xabd92248,0xbb6ebb30,0x35f13705,0xbbd4bbed,0xb2a1b04e,0xbbc9bba0,0x336534d5,0xbb80bbaf,0xb593b475,
0x39723996,0x39dc39ba,0x3832385d,0x3ad03ab5,0x3927394d,0x3a1f39fe,0x37b73807,0x3b023ae9,0x38d83900,0x3a5e3a3f,0x3705375e,0x3b303b1a,0x388738b0,0x3a993a7c,0x364e36aa,0x3b5a3b46,
0x36aa3b5a,0x3b46b64e,0x38b03a99,0x3a7cb887,0xb75ebb30,0xbb1a3705,0xb900ba5e,0xba3f38d8,0x38073b02,0x3ae9b7b7,0x394d3a1f,0x39feb927,0xb85dbad0,0xbab53832,0xb996b9dc,0xb9ba3972,
0x3475bb80,0xbbafb593,0xb4d5bbc9,0xbba03365,0xb04e3bd4,0x3bed32a1,0x37053b6e,0x3b30b5f1,0xa248bbfc,0xbc00abd9,0xb887bae9,0xba993807,0x31153bf8,0x3be6ad7e,0x39723a3f,0x39dcb900,
0xbab53705,0x385d3b30,0xa2483bed,0x3c00304e,0x3972b927,0xb9dcba1f,0xb365bbf4,0xbbc92f0e,0xb7b73a7c,0x3b0238b0,0x375e3b80,0x3b1ab593,0x3414bb6e,0xbbbcb5f1,0xb94dba99,0xb9fe3887,
0x3bed34d5,0x304ebba0,0x3534bb02,0xbb91b7b7,0xbbd428b6,0x32a13bff,0x22483be6,0x3c003115,0x3ad0b5f1,0xb832bb6e,0xb593bbdd,0xbb8031db,0xb900394d,0x3a3f39fe,0x39273ae9,0x3a1fb807,
0xb94dbb02,0xb9fe37b7,0xb8d83927,0x3a5e3a1f,0x3b5a38b0,0x364eba7c,0x32a1bb46,0xbbd4b6aa,0xbbffb1db,0x28b63bdd,0x33653c00,0x3bc9a248,0x3b1ab414,0xb75ebbbc,0xb900bb30,0xba3f3705,
0x22483bbc,0x3c003414,0x3a99b534,0xb887bb91,0xb832bbaf,0xbad03475,0xb6aa3a1f,0x3b463927,0x3b1a3972,0x375eb9dc,0xaf0ebbe6,0xbbf4b115,0xbbfcb2a1,0x2bd93bd4,0x38d83b6e,0x3a5eb5f1,
0x3927b832,0xba1fbad0,0xbbafa8b6,0x34753bff,0xabd93b6e,0x3bfc35f1,0x38d8b887,0xba5eba99,0xb85dbbbc,0xbab53414,0xa2483b91,0x3c003534,0x3b803900,0x3593ba3f,0xb8b0bba0,0xba7c34d5,
0xbbe6b2a1,0x31153bd4,0x3bff364e,0x28b6bb5a,0x3900b807,0xba3fbae9,0xba1f3534,0x39273b91,0x2bd93ba0,0x3bfc34d5,0x304ebb02,0xbbedb7b7,0xb9babb46,0xb99636aa,0x38873bc9,0x3a99b365,
0x3ad03a99,0x3832b887,0xbb80b996,0xb59339ba,0xbbafb04e,0x34753bed,0x3b1aabd9,0xb75ebbfc,0x3705b927,0xbb30ba1f,0xb4143a3f,0x3bbc3900,0x35f13bff,0x3b6e28b6,0xb85dbbe6,0xbab53115,
0xb4d5bbe6,0xbba0b115,0x3a3f3b46,0x3900b6aa,0x3b9139ba,0x3534b996,0xbbbcb2a1,0x34143bd4,0xba99304e,0x38873bed,0x35f1b94d,0xbb6eb9fe,0x28b6bb02,0xbbffb7b7,0x38323bf8,0x3ad0ad7e,
0xb64e38d8,0x3b5a3a5e,0xb85dbbfc,0xbab52bd9,0xb8b0bbf4,0xba7c2f0e,0x3bff375e,0xa8b6bb1a,0x3bf836aa,0xad7ebb46,0xb7b73832,0x3b023ad0,0xb7053887,0x3b303a99,0xb807bc00,0xbae92248,
0x3b302f0e,0xb705bbf4,0x34143ba0,0x3bbc34d5,0x22483ad0,0x3c003832,0xbbddb972,0xb1db39dc,0xbb46bab5,0xb6aa385d,0x38b0b5f1,0xba7cbb6e,0x3a1fb04e,0xb927bbed,0x37b73bfc,0x3b022bd9,
0xbbbcba1f,0xb4143927,0x2bd9ba3f,0xbbfcb900,0x3887b593,0xba99bb80,0x3b5a3ad0,0x364eb832,0x38b03c00,0x3a7ca248,0xb97232a1,0x39dc3bd4,0xbbafb534,0x34753b91,0xb75ebbed,0xbb1ab04e,
0x38873bfc,0x3a992bd9,0xb5f13807,0x3b6e3ae9,0xbb80b4d5,0x35933ba0,0xba7cbbaf,0xb8b03475,0xaf0ebad0,0xbbf4b832,0x3a1fa8b6,0xb927bbff,0x3bed39ba,0x304eb996,0x37053bd4,0x3b3032a1,
0x2f0eb972,0xbbf4b9dc,0x3927b115,0xba1fbbe6,0x3bbc3a99,0x3414b887,0x394d3c00,0x39fea248,0xb64e3705,0x3b5a3b30,0xbab5b04e,0x385d3bed,0xbad0bba0,0xb83234d5,0xb6aabbaf,0xbb46b475,
0xb9dca248,0x39723c00,0xbad0b2a1,0x38323bd4,0xb927bbfc,0xba1fabd9,0xb7b7bbbc,0xbb02b414,0x3a5e2f0e,0xb8d8bbf4,0x3b3034d5,0xb705bba0,0x38873be6,0x3a993115,0x364e3b80,0x3b5a3593,
0x3bff3996,0xa8b6b9ba,0x3bc9385d,0xb365bab5,0x2d7e39fe,0x3bf8394d,0x34753ae9,0x3baf3807,0xbbedb900,0x304e3a3f,0xbb91b75e,0x35343b1a,0xb1dbba7c,0xbbddb8b0,0xb5f1bb46,0xbb6eb6aa,
0xba3fbbff,0xb90028b6,0xbbf8ba7c,0xad7e38b0,0x3807b1db,0xbae9bbdd,0xabd9b996,0xbbfcb9ba,0x3b6e3b91,0x35f1b534,0x3bd438d8,0xb2a1ba5e,0xb365375e,0x3bc93b1a,0x35933b02,0x3b8037b7,
0x31db39fe,0x3bdd394d,0x3b5a3bbc,0x364eb414,0xbb46b75e,0x36aa3b1a,0xb11537b7,0x3be63b02,0xb900bbc9,0xba3fb365,0xbbf8b9dc,0x2d7e3972,0x38d8a248,0xba5ebc00,0xb534bab5,0xbb91b85d,
0x3807ad7e,0xbae9bbf8,0xb9febbf4,0xb94daf0e,0x3bdd3b46,0x31dbb6aa,0x35f1b365,0xbb6ebbc9,0x31153996,0x3be639ba,0x3bff3ab5,0x28b6b85d,0xbb02b705,0x37b73b30,0x34d53a5e,0x3ba038d8,
0xbb91b900,0x35343a3f,0x38073b1a,0x3ae9375e,0xb996bbc9,0xb9bab365,0xb887a8b6,0x3a993bff,0x3593b2a1,0xbb80bbd4,0xbbe6bb5a,0xb115364e,0x3bf83a5e,0xad7eb8d8,0xb475b9fe,0xbbafb94d,
0x3b6e3bed,0x35f1b04e,0xb2a1b94d,0xbbd4b9fe,0x31153900,0x3be63a3f,0x39dc34d5,0xb972bba0,0xba1fb593,0x39273b80,0x3baf3bc9,0x3475b365,0xbb91bbdd,0xb53431db,0x34143996,0x3bbc39ba,
0xb75eba7c,0xbb1ab8b0,0xaf0e3593,0x3bf43b80,0x3705a248,0xbb30bc00,0xbae9b85d,0x38073ab5,0x3bdd3a5e,0xb1dbb8d8,0xbb5abbfc,0xb64e2bd9,0x39dc3baf,0x39723475,0xb365b927,0xbbc9ba1f,
0xb36531db,0x3bc93bdd,0x36aa2248,0xbb46bc00,0xbb02b8d8,0x37b73a5e,0x3ba039fe,0xb4d5b94d,0xbb91bbf8,0xb5342d7e,0x3ae93bf4,0x38072f0e,0xb64eb9dc,0xbb5ab972,0x32a138b0,0x3bd43a7c,
0x3a7c385d,0xb8b0bab5,0xb972b5f1,0x39dc3b6e,0x3bf43bbc,0x2f0eb414,0xbbf8bb30,0x2d7e3705,0x394d3b1a,0x39fe375e,0xba5ebbaf,0xb8d8b475,0xa2483593,0x3c003b80,0xb1dbb832,0xbbddbad0,
0xbbf8bbc9,0xad7e3365,0x3b023972,0xb7b7b9dc,0xb9febb5a,0xb94db64e,0x3bed3bdd,0x304eb1db,0xb2a1b807,0xbbd4bae9,0x39ba3b30,0x39963705,0x36aa2f0e,0xbb46bbf4,0x3115375e,0x3be63b1a,
0x39963ae9,0x39ba3807,0xbbddbb30,0x31db3705,0x336537b7,0x3bc93b02,0xbb80bbf8,0xb593ad7e,0xb4d5a8b6,0x3ba03bff,0xb900ba7c,0xba3fb8b0,0xb9feb85d,0x394d3ab5,0xb04eb64e,0xbbedbb5a,
0xabd9b475,0xbbfcbbaf,0x3bed3bf8,0x304ead7e,0x35f13115,0xbb6ebbe6,0x3ab53b80,0x385d3593,0x39dc3887,0xb972ba99,0x38323996,0x3ad039ba,0x3ba03ae9,0xb4d5b807,0x2f0e3534,0x3bf43b91,
0xb8d8b75e,0x3a5e3b1a,0xbb30bbaf,0xb705b475,0xbab5b9dc,0x385d3972,0xb996ba7c,0xb9bab8b0,0xbbc9bb5a,0x3365364e,0xb6aab887,0xbb46ba99,0xbbf4bbfc,0xaf0e2bd9,0xad7eb414,0xbbf8bbbc,
0x3bd43b91,0xb2a1b534,0x39ba3a5e,0x399638d8,0x3bff3bf8,0x28b6ad7e,0x38323900,0x3ad03a3f,0x3baf3be6,0x34753115,0x34d536aa,0x3ba03b46,0x3ae93b5a,0x3807364e,0x2bd931db,0x3bfc3bdd,
0xbb02bb46,0xb7b7b6aa,0xb75eb832,0xbb1abad0,0xba5ebab5,0xb8d8b85d,0xb534b64e,0xbb91bb5a,0xb996b9fe,0xb9bab94d,0xb1dbb414,0xbbddbbbc,0xb8b0b927,0xba7cba1f,0xa8b6af0e,0xbbffbbf4,
0x359335f1,0x3b803b6e,0x311531db,0x3be63bdd,0x34d53534,0x3ba03b91,0x2f0e304e,0x3bf43bed,0x34143475,0x3bbc3baf,0x2bd92d7e,0x3bfc3bf8,0x32a13365,0x3bd43bc9,0x224828b6,0x3c003bff,
0x80000,0x180010,0xc0004,0x1c0014,0x280020,0x380030,0x2c0024,0x3c0034,0x480040,0x580050,0x4c0044,0x5c0054,0x680060,0x780070,0x6c0064,0x7c0074,
0x8c0084,0x9c0094,0x900088,0xa00098,0xac00a4,0xbc00b4,0xb000a8,0xc000b8,0xcc00c4,0xdc00d4,0xd000c8,0xe000d8,0xec00e4,0xfc00f4,0xf000e8,0x10000f8,
0x1100108,0x1200118,0x114010c,0x124011c,0x1300128,0x1400138,0x134012c,0x144013c,0x1500148,0x1600158,0x154014c,0x164015c,0x1700168,0x1800178,0x174016c,0x184017c,
0x194018c,0x1a4019c,0x1980190,0x1a801a0,0x1b401ac,0x1c401bc,0x1b801b0,0x1c801c0,0x1d401cc,0x1e401dc,0x1d801d0,0x1e801e0,0x1f401ec,0x20401fc,0x1f801f0,0x2080200,
0x2180210,0x2280220,0x21c0214,0x22c0224,0x2380230,0x2480240,0x23c0234,0x24c0244,0x2580250,0x2680260,0x25c0254,0x26c0264,0x2780270,0x2880280,0x27c0274,0x28c0284,
0x29c0294,0x2ac02a4,0x2a00298,0x2b002a8,0x2bc02b4,0x2cc02c4,0x2c002b8,0x2d002c8,0x2dc02d4,0x2ec02e4,0x2e002d8,0x2f002e8,0x2fc02f4,0x30c0304,0x30002f8,0x3100308,
0x3200318,0x3300328,0x324031c,0x334032c,0x3400338,0x3500348,0x344033c,0x354034c,0x3600358,0x3700368,0x364035c,0x374036c,0x3800378,0x3900388,0x384037c,0x394038c,
0x3a4039c,0x3b403ac,0x3a803a0,0x3b803b0,0x3c403bc,0x3d403cc,0x3c803c0,0x3d803d0,0x3e403dc,0x3f403ec,0x3e803e0,0x3f803f0,0x40403fc,0x414040c,0x4080400,0x4180410,
0x4240420,0x42c0428,0x4280420,0x4300428,0x4340430,0x43c0438,0x4380430,0x4400438,0x4440440,0x44c0448,0x4480440,0x4500448,0x4540450,0x45c0458,0x4580450,0x4600458,
0x4640460,0x46c0468,0x4680460,0x4700468,0x4740470,0x47c0478,0x4780470,0x4800478,0x4840480,0x48c0488,0x4880480,0x4900488,0x4940490,0x49c0498,0x4980490,0x4a40498,
0x4a804a4,0x4b004ac,0x4ac04a4,0x4b404ac,0x4b804b4,0x4c004bc,0x4bc04b4,0x4c404bc,0x4c804c4,0x4d004cc,0x4cc04c4,0x4d404cc,0x4d804d4,0x4e004dc,0x4dc04d4,0x4e404dc,
0x4e804e4,0x4f004ec,0x4ec04e4,0x4f404ec,0x4f804f4,0x50004fc,0x4fc04f4,0x50404fc,0x5080504,0x510050c,0x50c0504,0x514050c,0x5180514,0x520051c,0x51c0514,0x528051c,
0x52c0528,0x5340530,0x5300528,0x5380530,0x53c0538,0x5440540,0x5400538,0x5480540,0x54c0548,0x5540550,0x5500548,0x5580550,0x55c0558,0x5640560,0x5600558,0x5680560,
0x56c0568,0x5740570,0x5700568,0x5780570,0x57c0578,0x5840580,0x5800578,0x5880580,0x58c0588,0x5940590,0x5900588,0x5980590,0x59c0598,0x5a405a0,0x5a00598,0x5ac05a0,
0x5b005ac,0x5b805b4,0x5b405ac,0x5bc05b4,0x5c005bc,0x5c805c4,0x5c405bc,0x5cc05c4,0x5d005cc,0x5d805d4,0x5d405cc,0x5dc05d4,0x5e005dc,0x5e805e4,0x5e405dc,0x5ec05e4,
0x5f005ec,0x5f805f4,0x5f405ec,0x5fc05f4,0x60005fc,0x6080604,0x60405fc,0x60c0604,0x610060c,0x6180614,0x614060c,0x61c0614,0x620061c,0x6280624,0x624061c,0x6300624,
0x6300630,0x6380634,0x6340630,0x6380634,0x6380638,0x640063c,0x63c0638,0x640063c,0x6400640,0x6480644,0x6440640,0x6480644,0x6480648,0x650064c,0x64c0648,0x650064c,
0x6500650,0x6580654,0x6540650,0x6580654,0x6580658,0x660065c,0x65c0658,0x660065c,0x6600660,0x6680664,0x6640660,0x6680664,0x6680668,0x670066c,0x66c0668,0x670066c,
0x6700670,0x6780674,0x6740670,0x6780674,0x6780678,0x680067c,0x67c0678,0x680067c,0x6800680,0x6880684,0x6840680,0x6880684,0x6880688,0x690068c,0x68c0688,0x690068c,
0x6900690,0x6980694,0x6940690,0x6980694,0x6980698,0x6a0069c,0x69c0698,0x6a0069c,0x6a006a0,0x6a806a4,0x6a406a0,0x6a806a4,0x6a806a8,0x6b406ac,0x6ac06a8,0x6b406ac,
0x6b406b4,0x6bc06b8,0x6b806b4,0x6bc06b8,0x6bc06bc,0x6c406c0,0x6c006bc,0x6c406c0,0x6c406c4,0x6cc06c8,0x6c806c4,0x6cc06c8,0x6cc06cc,0x6d406d0,0x6d006cc,0x6d406d0,
0x6d406d4,0x6dc06d8,0x6d806d4,0x6dc06d8,0x6dc06dc,0x6e406e0,0x6e006dc,0x6e406e0,0x6e406e4,0x6ec06e8,0x6e806e4,0x6ec06e8,0x6ec06ec,0x6f406f0,0x6f006ec,0x6f406f0,
0x6f406f4,0x6fc06f8,0x6f806f4,0x6fc06f8,0x6fc06fc,0x7040700,0x70006fc,0x7040700,0x7040704,0x70c0708,0x7080704,0x70c0708,0x70c070c,0x7140710,0x710070c,0x7140710,
0x7140714,0x71c0718,0x7180714,0x71c0718,0x71c071c,0x7240720,0x720071c,0x7240720,0x7240724,0x72c0728,0x7280724,0x72c0728,0x72c072c,0x7380730,0x730072c,0x7380730,
0x7380738,0x740073c,0x73c0738,0x740073c,0x7400740,0x7480744,0x7440740,0x7480744,0x7480748,0x750074c,0x74c0748,0x750074c,0x7500750,0x7580754,0x7540750,0x7580754,
0x7580758,0x760075c,0x75c0758,0x760075c,0x7600760,0x7680764,0x7640760,0x7680764,0x7680768,0x770076c,0x76c0768,0x770076c,0x7700770,0x7780774,0x7740770,0x7780774,
0x7780778,0x780077c,0x77c0778,0x780077c,0x7800780,0x7880784,0x7840780,0x7880784,0x7880788,0x790078c,0x78c0788,0x790078c,0x7900790,0x7980794,0x7940790,0x7980794,
0x7980798,0x7a0079c,0x79c0798,0x7a0079c,0x7a007a0,0x7a807a4,0x7a407a0,0x7a807a4,0x7a807a8,0x7b007ac,0x7ac07a8,0x7b007ac,0x7b007b0,0x7bc07b4,0x7b407b0,0x7bc07b4,
0x7bc07bc,0x7c407c0,0x7c007bc,0x7c407c0,0x7c407c4,0x7cc07c8,0x7c807c4,0x7cc07c8,0x7cc07cc,0x7d407d0,0x7d007cc,0x7d407d0,0x7d407d4,0x7dc07d8,0x7d807d4,0x7dc07d8,
0x7dc07dc,0x7e407e0,0x7e007dc,0x7e407e0,0x7e407e4,0x7ec07e8,0x7e807e4,0x7ec07e8,0x7ec07ec,0x7f407f0,0x7f007ec,0x7f407f0,0x7f407f4,0x7fc07f8,0x7f807f4,0x7fc07f8,
0x7fc07fc,0x8040800,0x80007fc,0x8040800,0x8040804,0x80c0808,0x8080804,0x80c0808,0x80c080c,0x8140810,0x810080c,0x8140810,0x8140814,0x81c0818,0x8180814,0x81c0818,
0x81c081c,0x8240820,0x820081c,0x8240820,0x8240824,0x82c0828,0x8280824,0x82c0828,0x82c082c,0x8340830,0x830082c,0x8340830,0x8340834,0x8400838,0x8380834,0x8400838,
0xa3c0a3c,0xa400a3c,0xa3c0a3c,0xa400a40,0xa400a40,0xa440a44,0xa400a40,0xa440a44,0xa440a44,0xa480a44,0xa440a44,0xa480a48,0xa480a48,0xa500a50,0xa480a48,0xa500a50,
0xa2c0a2c,0xa300a2c,0xa2c0a2c,0xa300a30,0xa300a30,0xa340a34,0xa300a30,0xa340a34,0xa340a34,0xa380a34,0xa340a34,0xa380a38,0xa380a38,0xa3c0a3c,0xa380a38,0xa3c0a3c,
0xa1c0a1c,0xa200a1c,0xa1c0a1c,0xa200a20,0xa200a20,0xa240a24,0xa200a20,0xa240a24,0xa240a24,0xa280a24,0xa240a24,0xa280a28,0xa280a28,0xa2c0a2c,0xa280a28,0xa2c0a2c,
0xa0c0a0c,0xa100a0c,0xa0c0a0c,0xa100a10,0xa100a10,0xa140a14,0xa100a10,0xa140a14,0xa140a14,0xa180a14,0xa140a14,0xa180a18,0xa180a18,0xa1c0a1c,0xa180a18,0xa1c0a1c,
0x9fc09fc,0xa0009fc,0x9fc09fc,0xa000a00,0xa000a00,0xa040a04,0xa000a00,0xa040a04,0xa040a04,0xa080a04,0xa040a04,0xa080a08,0xa080a08,0xa0c0a0c,0xa080a08,0xa0c0a0c,
0x9ec09ec,0x9f009ec,0x9ec09ec,0x9f009f0,0x9f009f0,0x9f409f4,0x9f009f0,0x9f409f4,0x9f409f4,0x9f809f4,0x9f409f4,0x9f809f8,0x9f809f8,0x9fc09fc,0x9f809f8,0x9fc09fc,
0x9dc09dc,0x9e009dc,0x9dc09dc,0x9e009e0,0x9e009e0,0x9e409e4,0x9e009e0,0x9e409e4,0x9e409e4,0x9e809e4,0x9e409e4,0x9e809e8,0x9e809e8,0x9ec09ec,0x9e809e8,0x9ec09ec,
0x9cc09cc,0x9d009cc,0x9cc09cc,0x9d009d0,0x9d009d0,0x9d409d4,0x9d009d0,0x9d409d4,0x9d409d4,0x9d809d4,0x9d409d4,0x9d809d8,0x9d809d8,0x9dc09dc,0x9d809d8,0x9dc09dc,
0x9b809b8,0x9bc09b8,0x9b809b8,0x9bc09bc,0x9bc09bc,0x9c009c0,0x9bc09bc,0x9c009c0,0x9c009c0,0x9c409c0,0x9c009c0,0x9c409c4,0x9c409c4,0x9cc09cc,0x9c409c4,0x9cc09cc,
0x9a809a8,0x9ac09a8,0x9a809a8,0x9ac09ac,0x9ac09ac,0x9b009b0,0x9ac09ac,0x9b009b0,0x9b009b0,0x9b409b0,0x9b009b0,0x9b409b4,0x9b409b4,0x9b809b8,0x9b409b4,0x9b809b8,
0x9980998,0x99c0998,0x9980998,0x99c099c,0x99c099c,0x9a009a0,0x99c099c,0x9a009a0,0x9a009a0,0x9a409a0,0x9a009a0,0x9a409a4,0x9a409a4,0x9a809a8,0x9a409a4,0x9a809a8,
0x9880988,0x98c0988,0x9880988,0x98c098c,0x98c098c,0x9900990,0x98c098c,0x9900990,0x9900990,0x9940990,0x9900990,0x9940994,0x9940994,0x9980998,0x9940994,0x9980998,
0x9780978,0x97c0978,0x9780978,0x97c097c,0x97c097c,0x9800980,0x97c097c,0x9800980,0x9800980,0x9840980,0x9800980,0x9840984,0x9840984,0x9880988,0x9840984,0x9880988,
0x9680968,0x96c0968,0x9680968,0x96c096c,0x96c096c,0x9700970,0x96c096c,0x9700970,0x9700970,0x9740970,0x9700970,0x9740974,0x9740974,0x9780978,0x9740974,0x9780978,
0x9580958,0x95c0958,0x9580958,0x95c095c,0x95c095c,0x9600960,0x95c095c,0x9600960,0x9600960,0x9640960,0x9600960,0x9640964,0x9640964,0x9680968,0x9640964,0x9680968,
0x9480948,0x94c0948,0x9480948,0x94c094c,0x94c094c,0x9500950,0x94c094c,0x9500950,0x9500950,0x9540950,0x9500950,0x9540954,0x9540954,0x9580958,0x9540954,0x9580958,
0x9340934,0x9380934,0x9340934,0x9380938,0x9380938,0x93c093c,0x9380938,0x93c093c,0x93c093c,0x940093c,0x93c093c,0x9400940,0x9400940,0x9480948,0x9400940,0x9480948,
0x9240924,0x9280924,0x9240924,0x9280928,0x9280928,0x92c092c,0x9280928,0x92c092c,0x92c092c,0x930092c,0x92c092c,0x9300930,0x9300930,0x9340934,0x9300930,0x9340934,
0x9140914,0x9180914,0x9140914,0x9180918,0x9180918,0x91c091c,0x9180918,0x91c091c,0x91c091c,0x920091c,0x91c091c,0x9200920,0x9200920,0x9240924,0x9200920,0x9240924,
0x9040904,0x9080904,0x9040904,0x9080908,0x9080908,0x90c090c,0x9080908,0x90c090c,0x90c090c,0x910090c,0x90c090c,0x9100910,0x9100910,0x9140914,0x9100910,0x9140914,
0x8f408f4,0x8f808f4,0x8f408f4,0x8f808f8,0x8f808f8,0x8fc08fc,0x8f808f8,0x8fc08fc,0x8fc08fc,0x90008fc,0x8fc08fc,0x9000900,0x9000900,0x9040904,0x9000900,0x9040904,
0x8e408e4,0x8e808e4,0x8e408e4,0x8e808e8,0x8e808e8,0x8ec08ec,0x8e808e8,0x8ec08ec,0x8ec08ec,0x8f008ec,0x8ec08ec,0x8f008f0,0x8f008f0,0x8f408f4,0x8f008f0,0x8f408f4,
0x8d408d4,0x8d808d4,0x8d408d4,0x8d808d8,0x8d808d8,0x8dc08dc,0x8d808d8,0x8dc08dc,0x8dc08dc,0x8e008dc,0x8dc08dc,0x8e008e0,0x8e008e0,0x8e408e4,0x8e008e0,0x8e408e4,
0x8c408c4,0x8c808c4,0x8c408c4,0x8c808c8,0x8c808c8,0x8cc08cc,0x8c808c8,0x8cc08cc,0x8cc08cc,0x8d008cc,0x8cc08cc,0x8d008d0,0x8d008d0,0x8d408d4,0x8d008d0,0x8d408d4,
0x8b008b0,0x8b408b0,0x8b008b0,0x8b408b4,0x8b408b4,0x8b808b8,0x8b408b4,0x8b808b8,0x8b808b8,0x8bc08b8,0x8b808b8,0x8bc08bc,0x8bc08bc,0x8c408c4,0x8bc08bc,0x8c408c4,
0x8a008a0,0x8a408a0,0x8a008a0,0x8a408a4,0x8a408a4,0x8a808a8,0x8a408a4,0x8a808a8,0x8a808a8,0x8ac08a8,0x8a808a8,0x8ac08ac,0x8ac08ac,0x8b008b0,0x8ac08ac,0x8b008b0,
0x8900890,0x8940890,0x8900890,0x8940894,0x8940894,0x8980898,0x8940894,0x8980898,0x8980898,0x89c0898,0x8980898,0x89c089c,0x89c089c,0x8a008a0,0x89c089c,0x8a008a0,
0x8800880,0x8840880,0x8800880,0x8840884,0x8840884,0x8880888,0x8840884,0x8880888,0x8880888,0x88c0888,0x8880888,0x88c088c,0x88c088c,0x8900890,0x88c088c,0x8900890,
0x8700870,0x8740870,0x8700870,0x8740874,0x8740874,0x8780878,0x8740874,0x8780878,0x8780878,0x87c0878,0x8780878,0x87c087c,0x87c087c,0x8800880,0x87c087c,0x8800880,
0x8600860,0x8640860,0x8600860,0x8640864,0x8640864,0x8680868,0x8640864,0x8680868,0x8680868,0x86c0868,0x8680868,0x86c086c,0x86c086c,0x8700870,0x86c086c,0x8700870,
0x8500850,0x8540850,0x8500850,0x8540854,0x8540854,0x8580858,0x8540854,0x8580858,0x8580858,0x85c0858,0x8580858,0x85c085c,0x85c085c,0x8600860,0x85c085c,0x8600860,
0x8400840,0x8440840,0x8400840,0x8440844,0x8440844,0x8480848,0x8440844,0x8480848,0x8480848,0x84c0848,0x8480848,0x84c084c,0x84c084c,0x8500850,0x84c084c,0x8500850,
0x30003000,0x30003000,0x30003000,0x30003000,0x30003000,0x30003000,0x30003000,0x30003000,0x0,0x0,0x0,0x0,0x0,0x0,0x0,0x0,
0x30003000,0x30003000,0x30003000,0x30003000,0x30003000,0x30003000,0x30003000,0x30003000,0x0,0x0,0x0,0x0,0x0,0x0,0x0,0x0,
0x2a1f2da8,0xaf64ada8,0xaa1fada8,0x2f642da8,0x2f643000,0xaa1f0000,0xaf64b000,0x2a1f8000,0x2f642da8,0x2a1f2da8,0xaf64ada8,0xaa1fada8,0x2a1f0000,0x2f643000,0xaa1f0000,0xaf64b000,
0x263e2c72,0xafd9aea7,0xa63eac72,0x2fd92ea7,0x2ea72fd9,0xac72a63e,0xaea7afd9,0x2c72263e,0x2fd92ea7,0x263e2c72,0xafd9aea7,0xa63eac72,0x2c72263e,0x2ea72fd9,0xac72a63e,0xaea7afd9,
0x2da80000,0xada80000,0x2da88000,0xada80000,0x2da83000,0xada8b000,0x2da83000,0xada8b000,0x2da83000,0xada8b000,0x2da83000,0xada8b000,0xada80000,0x2da88000,0xada80000,0x2da88000,
0x2f642a1f,0xaf64aa1f,0x2f642a1f,0xaf64aa1f,0x2a1f2f64,0xaa1faf64,0x2a1f2f64,0xaa1faf64,0x2a1f2f64,0xaa1faf64,0x2a1f2f64,0xaa1faf64,0xaf64aa1f,0x2f642a1f,0xaf64aa1f,0x2f642a1f,
0xaa1f2da8,0x2f642da8,0x2a1fada8,0xaf64ada8,0x2f640000,0xaa1fb000,0xaf640000,0x2a1f3000,0xaf64ada8,0xaa1f2da8,0x2f642da8,0x2a1fada8,0x2a1f3000,0x2f648000,0xaa1fb000,0xaf640000,
0xaea7263e,0x2c722fd9,0x2ea7a63e,0xac72afd9,0x2fd92c72,0x263eaea7,0xafd9ac72,0xa63e2ea7,0xac72afd9,0xaea7263e,0x2c722fd9,0x2ea7a63e,0xa63e2ea7,0x2fd92c72,0x263eaea7,0xafd9ac72,
0xada82da8,0xada82da8,0xada82da8,0xada82da8,0x2da8ada8,0x2da8ada8,0x2da8ada8,0x2da8ada8,0x2da82da8,0x2da82da8,0x2da82da8,0x2da82da8,0xada8ada8,0xada8ada8,0xada8ada8,0xada8ada8,
0x3000,0x3000,0x3000,0x80003000,0x8000b000,0x8000b000,0x8000b000,0x8000b000,0x30000000,0x30008000,0x30008000,0x30008000,0xb0000000,0xb0000000,0xb0000000,0xb0000000,
0x2ea7263e,0xac722fd9,0xaea7a63e,0x2c72afd9,0xafd92c72,0xa63eaea7,0x2fd9ac72,0x263e2ea7,0x2c72afd9,0x2ea7263e,0xac722fd9,0xaea7a63e,0x263e2ea7,0xafd92c72,0xa63eaea7,0x2fd9ac72,
0x2f64ada8,0x2a1f2da8,0xaf642da8,0xaa1fada8,0xaa1f3000,0xaf640000,0x2a1fb000,0x2f648000,0xaa1fada8,0x2f64ada8,0x2a1f2da8,0xaf642da8,0x2f640000,0xaa1f3000,0xaf640000,0x2a1fb000,
0xaa1f2f64,0x2a1faf64,0xaa1f2f64,0x2a1faf64,0x2f64aa1f,0xaf642a1f,0x2f64aa1f,0xaf642a1f,0xaf642a1f,0x2f64aa1f,0xaf642a1f,0x2f64aa1f,0xaa1f2f64,0x2a1faf64,0xaa1f2f64,0x2a1faf64,
0x2da80000,0xada80000,0x2da88000,0xada80000,0x2da8b000,0xada83000,0x2da8b000,0xada83000,0xada83000,0x2da8b000,0xada83000,0x2da8b000,0x2da88000,0xada80000,0x2da88000,0xada88000,
0xa63e2c72,0x2fd9aea7,0x263eac72,0xafd92ea7,0xaea72fd9,0x2c72a63e,0x2ea7afd9,0xac72263e,0xafd92ea7,0xa63e2c72,0x2fd9aea7,0x263eac72,0xac72263e,0xaea72fd9,0x2c72a63e,0x2ea7afd9,
0x2f64ada8,0x2a1fada8,0xaf642da8,0xaa1f2da8,0x2a1f0000,0x2f64b000,0xaa1f0000,0xaf643000,0xaa1f2da8,0x2f64ada8,0x2a1fada8,0xaf642da8,0xaf643000,0x2a1f8000,0x2f64b000,0xaa1f8000,
0xb0003000,0xb0003000,0xb0003000,0xb0003000,0xb0003000,0xb0003000,0xb0003000,0xb0003000,0x0,0x8000,0x8000,0x80008000,0x8000,0x8000,0x8000,0x8000,
0x80000000,0x80000000,0x80008000,0x80008000,0x80000000,0x80008000,0x80008000,0x80008000,0xb0003000,0xb0003000,0xb0003000,0xb0003000,0xb0003000,0xb0003000,0xb0003000,0xb0003000,
0xaa1f2da8,0x2f64ada8,0x2a1fada8,0xaf642da8,0xaf643000,0x2a1f0000,0x2f64b000,0xaa1f8000,0xaf642da8,0xaa1f2da8,0x2f64ada8,0x2a1fada8,0xaa1f0000,0xaf643000,0x2a1f0000,0x2f64b000,
0x2fd9aea7,0x263eac72,0xafd92ea7,0xa63e2c72,0x2c72a63e,0x2ea7afd9,0xac72263e,0xaea72fd9,0xa63e2c72,0x2fd9aea7,0x263eac72,0xafd92ea7,0xaea72fd9,0x2c72a63e,0x2ea7afd9,0xac72263e,
0xada80000,0x2da80000,0xada88000,0x2da80000,0xada83000,0x2da8b000,0xada83000,0x2da8b000,0xada83000,0x2da8b000,0xada83000,0x2da8b000,0x2da80000,0xada88000,0x2da88000,0xada88000,
0xaa1f2f64,0x2a1faf64,0xaa1f2f64,0x2a1faf64,0x2f64aa1f,0xaf642a1f,0x2f64aa1f,0xaf642a1f,0x2f64aa1f,0xaf642a1f,0x2f64aa1f,0xaf642a1f,0x2a1faf64,0xaa1f2f64,0x2a1faf64,0xaa1f2f64,
0x2a1f2da8,0xaf642da8,0xaa1fada8,0x2f64ada8,0xaf640000,0x2a1fb000,0x2f640000,0xaa1f3000,0x2f64ada8,0x2a1f2da8,0xaf642da8,0xaa1fada8,0xaa1f3000,0xaf648000,0x2a1fb000,0x2f640000,
0x2c72afd9,0x2ea7263e,0xac722fd9,0xaea7a63e,0x263e2ea7,0xafd92c72,0xa63eaea7,0x2fd9ac72,0xaea7a63e,0x2c72afd9,0x2ea7263e,0xac722fd9,0x2fd9ac72,0x263e2ea7,0xafd92c72,0xa63eaea7,
0x2da8ada8,0x2da8ada8,0x2da8ada8,0x2da8ada8,0xada82da8,0xada82da8,0xada82da8,0xada82da8,0x2da82da8,0x2da82da8,0x2da82da8,0x2da82da8,0xada8ada8,0xada8ada8,0xada8ada8,0xada8ada8,
0x80003000,0x80003000,0x80003000,0x3000,0xb000,0x8000b000,0xb000,0xb000,0xb0000000,0xb0008000,0xb0008000,0xb0008000,0x30000000,0x30000000,0x30000000,0x30008000,
0x2c722fd9,0x2ea7a63e,0xac72afd9,0xaea7263e,0x263eaea7,0xafd9ac72,0xa63e2ea7,0x2fd92c72,0xaea7263e,0x2c722fd9,0x2ea7a63e,0xac72afd9,0x2fd92c72,0x263eaea7,0xafd9ac72,0xa63e2ea7,
0xaf64ada8,0xaa1f2da8,0x2f642da8,0x2a1fada8,0x2a1f3000,0x2f648000,0xaa1fb000,0xaf648000,0x2a1fada8,0xaf64ada8,0xaa1f2da8,0x2f642da8,0xaf640000,0x2a1f3000,0x2f648000,0xaa1fb000,
0x2f642a1f,0xaf64aa1f,0x2f642a1f,0xaf64aa1f,0x2a1f2f64,0xaa1faf64,0x2a1f2f64,0xaa1faf64,0xaa1faf64,0x2a1f2f64,0xaa1faf64,0x2a1f2f64,0x2f642a1f,0xaf64aa1f,0x2f642a1f,0xaf64aa1f,
0xada80000,0x2da80000,0xada88000,0x2da88000,0xada8b000,0x2da83000,0xada8b000,0x2da83000,0x2da83000,0xada8b000,0x2da83000,0xada8b000,0xada88000,0x2da88000,0xada88000,0x2da80000,
0x2fd92ea7,0x263e2c72,0xafd9aea7,0xa63eac72,0x2c72263e,0x2ea72fd9,0xac72a63e,0xaea7afd9,0xa63eac72,0x2fd92ea7,0x263e2c72,0xafd9aea7,0xaea7afd9,0x2c72263e,0x2ea72fd9,0xac72a63e,
0xaf64ada8,0xaa1fada8,0x2f642da8,0x2a1f2da8,0xaa1f0000,0xaf64b000,0x2a1f0000,0x2f643000,0x2a1f2da8,0xaf64ada8,0xaa1fada8,0x2f642da8,0x2f643000,0xaa1f8000,0xaf64b000,0x2a1f0000,
0x80008000,0x80008000,0x80008000,0x80008000,0x80008000,0x80008000,0x80008000,0x80008000,0x30003000,0x30003000,0x30003000,0x30003000,0x30003000,0x30003000,0x30003000,0x30003000,
0x80008000,0x80008000,0x80008000,0x80008000,0x80008000,0x80008000,0x80008000,0x80008000,0x30003000,0x30003000,0x30003000,0x30003000,0x30003000,0x30003000,0x30003000,0x30003000,
0xaf64ada8,0xaa1fada8,0x2f642da8,0x2a1f2da8,0xaa1f8000,0xaf64b000,0x2a1f8000,0x2f643000,0x2a1f2da8,0xaf64ada8,0xaa1fada8,0x2f642da8,0x2f643000,0xaa1f0000,0xaf64b000,0x2a1f8000,
0xafd9aea7,0xa63eac72,0x2fd92ea7,0x263e2c72,0xac72a63e,0xaea7afd9,0x2c72263e,0x2ea72fd9,0x263e2c72,0xafd9aea7,0xa63eac72,0x2fd92ea7,0x2ea72fd9,0xac72a63e,0xaea7afd9,0x2c72263e,
0x2da83000,0xada8b000,0x2da83000,0xada8b000,0xada80000,0x2da88000,0xada80000,0x2da88000,0xada88000,0x2da88000,0xada80000,0x2da88000,0xada8b000,0x2da83000,0xada8b000,0x2da83000,
0x2a1f2f64,0xaa1faf64,0x2a1f2f64,0xaa1faf64,0xaf64aa1f,0x2f642a1f,0xaf64aa1f,0x2f642a1f,0xaf64aa1f,0x2f642a1f,0xaf64aa1f,0x2f642a1f,0xaa1faf64,0x2a1f2f64,0xaa1faf64,0x2a1f2f64,
0xaf64ada8,0xaa1f2da8,0x2f642da8,0x2a1fada8,0x2a1f3000,0x2f648000,0xaa1fb000,0xaf640000,0x2a1fada8,0xaf64ada8,0xaa1f2da8,0x2f642da8,0xaf648000,0x2a1f3000,0x2f648000,0xaa1fb000,
0xac72afd9,0xaea7263e,0x2c722fd9,0x2ea7a63e,0xa63e2ea7,0x2fd92c72,0x263eaea7,0xafd9ac72,0x2ea7a63e,0xac72afd9,0xaea7263e,0x2c722fd9,0xafd9ac72,0xa63e2ea7,0x2fd92c72,0x263eaea7,
0xada8ada8,0xada8ada8,0xada8ada8,0xada8ada8,0x2da82da8,0x2da82da8,0x2da82da8,0x2da82da8,0xada82da8,0xada82da8,0xada82da8,0xada82da8,0x2da8ada8,0x2da8ada8,0x2da8ada8,0x2da8ada8,
0xb0008000,0xb0000000,0xb0000000,0xb0000000,0x30008000,0x30008000,0x30008000,0x30008000,0x3000,0x3000,0x3000,0x80003000,0x8000b000,0x8000b000,0x8000b000,0x8000b000,
0xac722fd9,0xaea7a63e,0x2c72afd9,0x2ea7263e,0xa63eaea7,0x2fd9ac72,0x263e2ea7,0xafd92c72,0x2ea7263e,0xac722fd9,0xaea7a63e,0x2c72afd9,0xafd92c72,0xa63eaea7,0x2fd9ac72,0x263e2ea7,
0x2a1f2da8,0xaf642da8,0xaa1fada8,0x2f64ada8,0xaf648000,0x2a1fb000,0x2f648000,0xaa1f3000,0x2f64ada8,0x2a1f2da8,0xaf642da8,0xaa1fada8,0xaa1f3000,0xaf640000,0x2a1fb000,0x2f648000,
0xaf642a1f,0x2f64aa1f,0xaf642a1f,0x2f64aa1f,0xaa1f2f64,0x2a1faf64,0xaa1f2f64,0x2a1faf64,0x2a1faf64,0xaa1f2f64,0x2a1faf64,0xaa1f2f64,0xaf642a1f,0x2f64aa1f,0xaf642a1f,0x2f64aa1f,
0xada83000,0x2da8b000,0xada83000,0x2da8b000,0x2da88000,0xada80000,0x2da88000,0xada88000,0xada88000,0x2da88000,0xada80000,0x2da88000,0xada83000,0x2da8b000,0xada83000,0x2da8b000,
0xafd92ea7,0xa63e2c72,0x2fd9aea7,0x263eac72,0xac72263e,0xaea72fd9,0x2c72a63e,0x2ea7afd9,0x263eac72,0xafd92ea7,0xa63e2c72,0x2fd9aea7,0x2ea7afd9,0xac72263e,0xaea72fd9,0x2c72a63e,
0xaa1f2da8,0x2f64ada8,0x2a1fada8,0xaf642da8,0xaf643000,0x2a1f8000,0x2f64b000,0xaa1f8000,0xaf642da8,0xaa1f2da8,0x2f64ada8,0x2a1fada8,0xaa1f8000,0xaf643000,0x2a1f8000,0x2f64b000,
0x80008000,0x80000000,0x80000000,0x0,0x80000000,0x80000000,0x80000000,0x80000000,0xb0003000,0xb0003000,0xb0003000,0xb0003000,0xb0003000,0xb0003000,0xb0003000,0xb0003000,
0x3000b000,0x3000b000,0x3000b000,0x3000b000,0x3000b000,0x3000b000,0x3000b000,0x3000b000,0x80000000,0x80000000,0x80008000,0x80008000,0x80000000,0x80008000,0x80008000,0x80008000,
0x2f64ada8,0x2a1fada8,0xaf642da8,0xaa1f2da8,0x2a1f8000,0x2f64b000,0xaa1f8000,0xaf643000,0xaa1f2da8,0x2f64ada8,0x2a1fada8,0xaf642da8,0xaf643000,0x2a1f0000,0x2f64b000,0xaa1f8000,
0x263eac72,0xafd92ea7,0xa63e2c72,0x2fd9aea7,0x2ea7afd9,0xac72263e,0xaea72fd9,0x2c72a63e,0x2fd9aea7,0x263eac72,0xafd92ea7,0xa63e2c72,0x2c72a63e,0x2ea7afd9,0xac72263e,0xaea72fd9,
0xada83000,0x2da8b000,0xada83000,0x2da8b000,0x2da80000,0xada88000,0x2da88000,0xada88000,0x2da88000,0xada88000,0x2da80000,0xada88000,0x2da8b000,0xada83000,0x2da8b000,0xada83000,
0x2f64aa1f,0xaf642a1f,0x2f64aa1f,0xaf642a1f,0x2a1faf64,0xaa1f2f64,0x2a1faf64,0xaa1f2f64,0x2a1faf64,0xaa1f2f64,0x2a1faf64,0xaa1f2f64,0xaf642a1f,0x2f64aa1f,0xaf642a1f,0x2f64aa1f,
0x2f64ada8,0x2a1f2da8,0xaf642da8,0xaa1fada8,0xaa1f3000,0xaf648000,0x2a1fb000,0x2f640000,0xaa1fada8,0x2f64ada8,0x2a1f2da8,0xaf642da8,0x2f648000,0xaa1f3000,0xaf648000,0x2a1fb000,
0xaea7a63e,0x2c72afd9,0x2ea7263e,0xac722fd9,0x2fd9ac72,0x263e2ea7,0xafd92c72,0xa63eaea7,0xac722fd9,0xaea7a63e,0x2c72afd9,0x2ea7263e,0xa63eaea7,0x2fd9ac72,0x263e2ea7,0xafd92c72,
0xada8ada8,0xada8ada8,0xada8ada8,0xada8ada8,0x2da82da8,0x2da82da8,0x2da82da8,0x2da82da8,0x2da8ada8,0x2da8ada8,0x2da8ada8,0x2da8ada8,0xada82da8,0xada82da8,0xada82da8,0xada82da8,
0x30008000,0x30000000,0x30000000,0x30000000,0xb0008000,0xb0008000,0xb0008000,0xb0000000,0x80003000,0x80003000,0x80003000,0x3000,0xb000,0x8000b000,0xb000,0xb000,
0x2ea7a63e,0xac72afd9,0xaea7263e,0x2c722fd9,0xafd9ac72,0xa63e2ea7,0x2fd92c72,0x263eaea7,0x2c722fd9,0x2ea7a63e,0xac72afd9,0xaea7263e,0x263eaea7,0xafd9ac72,0xa63e2ea7,0x2fd92c72,
0xaa1f2da8,0x2f642da8,0x2a1fada8,0xaf64ada8,0x2f648000,0xaa1fb000,0xaf640000,0x2a1f3000,0xaf64ada8,0xaa1f2da8,0x2f642da8,0x2a1fada8,0x2a1f3000,0x2f648000,0xaa1fb000,0xaf648000,
0xaa1faf64,0x2a1f2f64,0xaa1faf64,0x2a1f2f64,0x2f642a1f,0xaf64aa1f,0x2f642a1f,0xaf64aa1f,0xaf64aa1f,0x2f642a1f,0xaf64aa1f,0x2f642a1f,0xaa1faf64,0x2a1f2f64,0xaa1faf64,0x2a1f2f64,
0x2da83000,0xada8b000,0x2da83000,0xada8b000,0xada88000,0x2da88000,0xada88000,0x2da80000,0x2da88000,0xada88000,0x2da80000,0xada80000,0x2da83000,0xada8b000,0x2da83000,0xada8b000,
0xa63eac72,0x2fd92ea7,0x263e2c72,0xafd9aea7,0xaea7afd9,0x2c72263e,0x2ea72fd9,0xac72a63e,0xafd9aea7,0xa63eac72,0x2fd92ea7,0x263e2c72,0xac72a63e,0xaea7afd9,0x2c72263e,0x2ea72fd9,
0x2a1f2da8,0xaf64ada8,0xaa1fada8,0x2f642da8,0x2f643000,0xaa1f8000,0xaf64b000,0x2a1f0000,0x2f642da8,0x2a1f2da8,0xaf64ada8,0xaa1fada8,0x2a1f8000,0x2f643000,0xaa1f8000,0xaf64b000,
0x3c003c00,0x3c003c00,0x3c003c00,0x3c003c00,0x3c003c00,0x3c003c00,0x3c003c00,0x3c003c00,0x80008000,0x80008000,0x80008000,0x80008000,0x80008000,0x80008000,0x80008000,0x80008000,
0x3bd93c00,0x3aa73b64,0x387239a8,0x323e361f,0xb23e0000,0xb872b61f,0xbaa7b9a8,0xbbd9bb64,0xb23e8000,0xb872b61f,0xbaa7b9a8,0xbbd9bb64,0xbbd9bc00,0xbaa7bb64,0xb872b9a8,0xb23eb61f,
0xbb64bc00,0xb61fb9a8,0x361f8000,0x3b6439a8,0x3b643c00,0x361f39a8,0xb61f0000,0xbb64b9a8,0x361f8000,0x3b6439a8,0x3b643c00,0x361f39a8,0xb61f8000,0xbb64b9a8,0xbb64bc00,0xb61fb9a8,
0x38728000,0x3bd93b64,0x323e39a8,0xbaa7b61f,0x3aa73c00,0xb23e361f,0xbbd9b9a8,0xb872bb64,0x3aa73c00,0xb23e361f,0xbbd9b9a8,0xb872bb64,0xb8728000,0xbbd9bb64,0xb23eb9a8,0x3aa7361f,
0xbc008000,0x3c008000,0xbc000000,0x3c008000,0xbc000000,0x3c008000,0xbc000000,0x3c008000,0x3c00,0x8000bc00,0x3c00,0x8000bc00,0x3c00,0x8000bc00,0x80003c00,0x8000bc00,
0xbbd98000,0x3aa7361f,0xb872b9a8,0x323e3b64,0x323ebc00,0xb8723b64,0x3aa7b9a8,0xbbd9361f,0xb23e3c00,0x3872bb64,0xbaa739a8,0x3bd9b61f,0xbbd90000,0x3aa7361f,0xb872b9a8,0x323e3b64,
0x3b648000,0xb61fb9a8,0xb61f3c00,0x3b64b9a8,0xbb648000,0x361f39a8,0x361fbc00,0xbb6439a8,0x361fbc00,0xbb6439a8,0x3b648000,0xb61fb9a8,0xb61f3c00,0x3b64b9a8,0xbb640000,0x361f39a8,
0xb8723c00,0x3bd9b61f,0xb23eb9a8,0xbaa73b64,0xbaa78000,0xb23e3b64,0x3bd9b9a8,0xb872b61f,0x3aa78000,0x323ebb64,0xbbd939a8,0x3872361f,0xb8723c00,0x3bd9b61f,0xb23eb9a8,0xbaa73b64,
0xbbd93c00,0xbaa73b64,0xb87239a8,0xb23e361f,0x323e8000,0x3872b61f,0x3aa7b9a8,0x3bd9bb64,0x323e8000,0x3872b61f,0x3aa7b9a8,0x3bd9bb64,0x3bd9bc00,0x3aa7bb64,0x3872b9a8,0x323eb61f,
0xbc003c00,0xbc003c00,0xbc003c00,0xbc003c00,0xbc003c00,0xbc003c00,0xbc003c00,0xbc003c00,0x80008000,0x80000000,0x80000000,0x80000000,0x80000000,0x80000000,0x0,0x80000000,
0xb8728000,0xbbd93b64,0xb23e39a8,0x3aa7b61f,0xbaa73c00,0x323e361f,0x3bd9b9a8,0x3872bb64,0xbaa73c00,0x323e361f,0x3bd9b9a8,0x3872bb64,0x38728000,0x3bd9bb64,0x323eb9a8,0xbaa7361f,
0x3b64bc00,0x361fb9a8,0xb61f8000,0xbb6439a8,0xbb643c00,0xb61f39a8,0x361f0000,0x3b64b9a8,0xb61f8000,0xbb6439a8,0xbb643c00,0xb61f39a8,0x361f8000,0x3b64b9a8,0x3b64bc00,0x361fb9a8,
0x3bd98000,0xbaa7361f,0x3872b9a8,0xb23e3b64,0xb23ebc00,0x38723b64,0xbaa7b9a8,0x3bd9361f,0x323e3c00,0xb872bb64,0x3aa739a8,0xbbd9b61f,0x3bd98000,0xbaa7361f,0x3872b9a8,0xb23e3b64,
0x3c008000,0xbc008000,0x3c000000,0xbc008000,0x3c000000,0xbc008000,0x3c000000,0xbc000000,0x80003c00,0xbc00,0x80003c00,0x8000bc00,0x80003c00,0xbc00,0x80003c00,0xbc00,
0x38723c00,0xbbd9b61f,0x323eb9a8,0x3aa73b64,0x3aa78000,0x323e3b64,0xbbd9b9a8,0x3872b61f,0xbaa78000,0xb23ebb64,0x3bd939a8,0xb872361f,0x38723c00,0xbbd9b61f,0x323eb9a8,0x3aa73b64,
0xbb640000,0x361fb9a8,0x361f3c00,0xbb64b9a8,0x3b648000,0xb61f39a8,0xb61fbc00,0x3b6439a8,0xb61fbc00,0x3b6439a8,0xbb640000,0x361fb9a8,0x361f3c00,0xbb64b9a8,0x3b648000,0xb61f39a8,
0x39a83c00,0xb9a80000,0xb9a8bc00,0x39a88000,0x39a83c00,0xb9a80000,0xb9a8bc00,0x39a88000,0xb9a88000,0xb9a8bc00,0x39a88000,0x39a83c00,0xb9a80000,0xb9a8bc00,0x39a88000,0x39a83c00,
0x38723c00,0xbbd9b61f,0x323eb9a8,0x3aa73b64,0xbaa70000,0xb23ebb64,0x3bd939a8,0xb872361f,0xbaa78000,0xb23ebb64,0x3bd939a8,0xb872361f,0xb872bc00,0x3bd9361f,0xb23e39a8,0xbaa7bb64,
0xb61fbc00,0x3b6439a8,0xbb640000,0x361fb9a8,0x361f3c00,0xbb64b9a8,0x3b648000,0xb61f39a8,0x3b648000,0xb61f39a8,0xb61fbc00,0x3b6439a8,0xbb648000,0x361fb9a8,0x361f3c00,0xbb64b9a8,
0x3bd98000,0xbaa7361f,0x3872b9a8,0xb23e3b64,0x323e3c00,0xb872bb64,0x3aa739a8,0xbbd9b61f,0x323e3c00,0xb872bb64,0x3aa739a8,0xbbd9b61f,0xbbd98000,0x3aa7b61f,0xb87239a8,0x323ebb64,
0xb9a88000,0xb9a83c00,0x39a88000,0x39a8bc00,0xb9a80000,0xb9a83c00,0x39a88000,0x39a8bc00,0xb9a83c00,0x39a88000,0x39a8bc00,0xb9a80000,0xb9a83c00,0x39a88000,0x39a8bc00,0xb9a88000,
0xb8728000,0xbbd93b64,0xb23e39a8,0x3aa7b61f,0x3aa7bc00,0xb23eb61f,0xbbd939a8,0xb8723b64,0xbaa73c00,0x323e361f,0x3bd9b9a8,0x3872bb64,0xb8728000,0xbbd93b64,0xb23e39a8,0x3aa7b61f,
0x361f8000,0x3b64b9a8,0x3b64bc00,0x361fb9a8,0xb61f8000,0xbb6439a8,0xbb643c00,0xb61f39a8,0x3b64bc00,0x361fb9a8,0xb61f8000,0xbb6439a8,0xbb643c00,0xb61f39a8,0x361f8000,0x3b64b9a8,
0xbbd93c00,0xbaa73b64,0xb87239a8,0xb23e361f,0xb23e8000,0xb872361f,0xbaa739a8,0xbbd93b64,0x323e8000,0x3872b61f,0x3aa7b9a8,0x3bd9bb64,0xbbd93c00,0xbaa73b64,0xb87239a8,0xb23e361f,
0xb8723c00,0x3bd9b61f,0xb23eb9a8,0xbaa73b64,0x3aa78000,0x323ebb64,0xbbd939a8,0x3872361f,0x3aa78000,0x323ebb64,0xbbd939a8,0x3872361f,0x3872bc00,0xbbd9361f,0x323e39a8,0x3aa7bb64,
0xb9a83c00,0x39a80000,0x39a8bc00,0xb9a88000,0xb9a83c00,0x39a88000,0x39a8bc00,0xb9a88000,0x39a88000,0x39a8bc00,0xb9a88000,0xb9a83c00,0x39a80000,0x39a8bc00,0xb9a88000,0xb9a83c00,
0xbbd98000,0x3aa7361f,0xb872b9a8,0x323e3b64,0xb23e3c00,0x3872bb64,0xbaa739a8,0x3bd9b61f,0xb23e3c00,0x3872bb64,0xbaa739a8,0x3bd9b61f,0x3bd98000,0xbaa7b61f,0x387239a8,0xb23ebb64,
0x361fbc00,0xbb6439a8,0x3b640000,0xb61fb9a8,0xb61f3c00,0x3b64b9a8,0xbb648000,0x361f39a8,0xbb648000,0x361f39a8,0x361fbc00,0xbb6439a8,0x3b648000,0xb61fb9a8,0xb61f3c00,0x3b64b9a8,
0x38728000,0x3bd93b64,0x323e39a8,0xbaa7b61f,0xbaa7bc00,0x323eb61f,0x3bd939a8,0x38723b64,0x3aa73c00,0xb23e361f,0xbbd9b9a8,0xb872bb64,0x38728000,0x3bd93b64,0x323e39a8,0xbaa7b61f,
0x39a88000,0x39a83c00,0xb9a88000,0xb9a8bc00,0x39a80000,0x39a83c00,0xb9a80000,0xb9a8bc00,0x39a83c00,0xb9a88000,0xb9a8bc00,0x39a88000,0x39a83c00,0xb9a88000,0xb9a8bc00,0x39a80000,
0x3bd93c00,0x3aa73b64,0x387239a8,0x323e361f,0x323e8000,0x3872361f,0x3aa739a8,0x3bd93b64,0xb23e8000,0xb872b61f,0xbaa7b9a8,0xbbd9bb64,0x3bd93c00,0x3aa73b64,0x387239a8,0x323e361f,
0xb61f8000,0xbb64b9a8,0xbb64bc00,0xb61fb9a8,0x361f8000,0x3b6439a8,0x3b643c00,0x361f39a8,0xbb64bc00,0xb61fb9a8,0x361f0000,0x3b6439a8,0x3b643c00,0x361f39a8,0xb61f8000,0xbb64b9a8,
0x0,0x0,0x0,0x0,0x0,0x0,0x0,0x0,0x3c003c00,0x3c003c00,0x3c003c00,0x3c003c00,0x3c003c00,0x3c003c00,0x3c003c00,0x3c003c00,
0x323e0000,0x3872361f,0x3aa739a8,0x3bd93b64,0x3bd93c00,0x3aa73b64,0x387239a8,0x323e361f,0x3bd93c00,0x3aa73b64,0x387239a8,0x323e361f,0xb23e0000,0xb872b61f,0xbaa7b9a8,0xbbd9bb64,
0xb61f0000,0xbb64b9a8,0xbb64bc00,0xb61fb9a8,0x361f0000,0x3b6439a8,0x3b643c00,0x361f39a8,0xbb64bc00,0xb61fb9a8,0x361f8000,0x3b6439a8,0x3b643c00,0x361f39a8,0xb61f0000,0xbb64b9a8,
0xbaa7bc00,0x323eb61f,0x3bd939a8,0x38723b64,0x38720000,0x3bd93b64,0x323e39a8,0xbaa7b61f,0x38728000,0x3bd93b64,0x323e39a8,0xbaa7b61f,0x3aa73c00,0xb23e361f,0xbbd9b9a8,0xb872bb64,
0x3c00,0x8000bc00,0x3c00,0x8000bc00,0x3c00,0x8000bc00,0x80003c00,0x8000bc00,0x3c000000,0xbc000000,0x3c008000,0xbc000000,0x3c008000,0xbc000000,0x3c008000,0xbc000000,
0xb23e3c00,0x3872bb64,0xbaa739a8,0x3bd9b61f,0xbbd90000,0x3aa7361f,0xb872b9a8,0x323e3b64,0x3bd90000,0xbaa7b61f,0x387239a8,0xb23ebb64,0xb23e3c00,0x3872bb64,0xbaa739a8,0x3bd9b61f,
0x361fbc00,0xbb6439a8,0x3b648000,0xb61fb9a8,0xb61f3c00,0x3b64b9a8,0xbb640000,0x361f39a8,0xbb640000,0x361f39a8,0x361fbc00,0xbb6439a8,0x3b640000,0xb61fb9a8,0xb61f3c00,0x3b64b9a8,
0x3aa78000,0x323ebb64,0xbbd939a8,0x3872361f,0xb8723c00,0x3bd9b61f,0xb23eb9a8,0xbaa73b64,0x3872bc00,0xbbd9361f,0x323e39a8,0x3aa7bb64,0x3aa70000,0x323ebb64,0xbbd939a8,0x3872361f,
0xb23e0000,0xb872361f,0xbaa739a8,0xbbd93b64,0xbbd93c00,0xbaa73b64,0xb87239a8,0xb23e361f,0xbbd93c00,0xbaa73b64,0xb87239a8,0xb23e361f,0x323e8000,0x3872b61f,0x3aa7b9a8,0x3bd9bb64,
0x0,0x8000,0x8000,0x8000,0x8000,0x8000,0x80008000,0x8000,0xbc003c00,0xbc003c00,0xbc003c00,0xbc003c00,0xbc003c00,0xbc003c00,0xbc003c00,0xbc003c00,
0x3aa7bc00,0xb23eb61f,0xbbd939a8,0xb8723b64,0xb8720000,0xbbd93b64,0xb23e39a8,0x3aa7b61f,0xb8728000,0xbbd93b64,0xb23e39a8,0x3aa7b61f,0xbaa73c00,0x323e361f,0x3bd9b9a8,0x3872bb64,
0x361f0000,0x3b64b9a8,0x3b64bc00,0x361fb9a8,0xb61f0000,0xbb6439a8,0xbb643c00,0xb61f39a8,0x3b64bc00,0x361fb9a8,0xb61f8000,0xbb6439a8,0xbb643c00,0xb61f39a8,0x361f0000,0x3b64b9a8,
0x323e3c00,0xb872bb64,0x3aa739a8,0xbbd9b61f,0x3bd98000,0xbaa7361f,0x3872b9a8,0xb23e3b64,0xbbd90000,0x3aa7b61f,0xb87239a8,0x323ebb64,0x323e3c00,0xb872bb64,0x3aa739a8,0xbbd9b61f,
0x80003c00,0xbc00,0x80003c00,0x8000bc00,0x80003c00,0xbc00,0x80003c00,0xbc00,0xbc000000,0x3c000000,0xbc008000,0x3c000000,0xbc008000,0x3c000000,0xbc008000,0x3c008000,
0xbaa78000,0xb23ebb64,0x3bd939a8,0xb872361f,0x38723c00,0xbbd9b61f,0x323eb9a8,0x3aa73b64,0xb872bc00,0x3bd9361f,0xb23e39a8,0xbaa7bb64,0xbaa70000,0xb23ebb64,0x3bd939a8,0xb872361f,
0xb61fbc00,0x3b6439a8,0xbb640000,0x361fb9a8,0x361f3c00,0xbb64b9a8,0x3b648000,0xb61f39a8,0x3b648000,0xb61f39a8,0xb61fbc00,0x3b6439a8,0xbb640000,0x361fb9a8,0x361f3c00,0xbb64b9a8,
0x39a80000,0x39a83c00,0xb9a80000,0xb9a8bc00,0x39a88000,0x39a83c00,0xb9a80000,0xb9a8bc00,0x39a83c00,0xb9a80000,0xb9a8bc00,0x39a88000,0x39a83c00,0xb9a80000,0xb9a8bc00,0x39a88000,
0x3aa70000,0x323e3b64,0xbbd9b9a8,0x3872b61f,0x38723c00,0xbbd9b61f,0x323eb9a8,0x3aa73b64,0x38723c00,0xbbd9b61f,0x323eb9a8,0x3aa73b64,0xbaa70000,0xb23ebb64,0x3bd939a8,0xb872361f,
0xbb640000,0x361fb9a8,0x361f3c00,0xbb64b9a8,0x3b640000,0xb61f39a8,0xb61fbc00,0x3b6439a8,0xb61fbc00,0x3b6439a8,0xbb640000,0x361fb9a8,0x361f3c00,0xbb64b9a8,0x3b648000,0xb61f39a8,
0xb23ebc00,0x38723b64,0xbaa7b9a8,0x3bd9361f,0x3bd90000,0xbaa7361f,0x3872b9a8,0xb23e3b64,0x3bd98000,0xbaa7361f,0x3872b9a8,0xb23e3b64,0x323e3c00,0xb872bb64,0x3aa739a8,0xbbd9b61f,
0xb9a83c00,0x39a88000,0x39a8bc00,0xb9a80000,0xb9a83c00,0x39a88000,0x39a8bc00,0xb9a88000,0x39a80000,0x39a8bc00,0xb9a80000,0xb9a83c00,0x39a88000,0x39a8bc00,0xb9a80000,0xb9a83c00,
0xbaa73c00,0x323e361f,0x3bd9b9a8,0x3872bb64,0xb8728000,0xbbd93b64,0xb23e39a8,0x3aa7b61f,0x38720000,0x3bd9bb64,0x323eb9a8,0xbaa7361f,0xbaa73c00,0x323e361f,0x3bd9b9a8,0x3872bb64,
0x3b64bc00,0x361fb9a8,0xb61f8000,0xbb6439a8,0xbb643c00,0xb61f39a8,0x361f8000,0x3b64b9a8,0xb61f0000,0xbb6439a8,0xbb643c00,0xb61f39a8,0x361f0000,0x3b64b9a8,0x3b64bc00,0x361fb9a8,
0x323e8000,0x3872b61f,0x3aa7b9a8,0x3bd9bb64,0xbbd93c00,0xbaa73b64,0xb87239a8,0xb23e361f,0x3bd9bc00,0x3aa7bb64,0x3872b9a8,0x323eb61f,0x323e0000,0x3872b61f,0x3aa7b9a8,0x3bd9bb64,
0xbaa70000,0xb23e3b64,0x3bd9b9a8,0xb872b61f,0xb8723c00,0x3bd9b61f,0xb23eb9a8,0xbaa73b64,0xb8723c00,0x3bd9b61f,0xb23eb9a8,0xbaa73b64,0x3aa78000,0x323ebb64,0xbbd939a8,0x3872361f,
0xb9a80000,0xb9a83c00,0x39a80000,0x39a8bc00,0xb9a88000,0xb9a83c00,0x39a80000,0x39a8bc00,0xb9a83c00,0x39a80000,0x39a8bc00,0xb9a88000,0xb9a83c00,0x39a88000,0x39a8bc00,0xb9a88000,
0x323ebc00,0xb8723b64,0x3aa7b9a8,0xbbd9361f,0xbbd90000,0x3aa7361f,0xb872b9a8,0x323e3b64,0xbbd98000,0x3aa7361f,0xb872b9a8,0x323e3b64,0xb23e3c00,0x3872bb64,0xbaa739a8,0x3bd9b61f,
0x3b640000,0xb61fb9a8,0xb61f3c00,0x3b64b9a8,0xbb640000,0x361f39a8,0x361fbc00,0xbb6439a8,0x361fbc00,0xbb6439a8,0x3b640000,0xb61fb9a8,0xb61f3c00,0x3b64b9a8,0xbb648000,0x361f39a8,
0x3aa73c00,0xb23e361f,0xbbd9b9a8,0xb872bb64,0x38728000,0x3bd93b64,0x323e39a8,0xbaa7b61f,0xb8720000,0xbbd9bb64,0xb23eb9a8,0x3aa7361f,0x3aa73c00,0xb23e361f,0xbbd9b9a8,0xb872bb64,
0x39a83c00,0xb9a88000,0xb9a8bc00,0x39a88000,0x39a83c00,0xb9a88000,0xb9a8bc00,0x39a80000,0xb9a80000,0xb9a8bc00,0x39a80000,0x39a83c00,0xb9a88000,0xb9a8bc00,0x39a88000,0x39a83c00,
0xb23e8000,0xb872b61f,0xbaa7b9a8,0xbbd9bb64,0x3bd93c00,0x3aa73b64,0x387239a8,0x323e361f,0xbbd9bc00,0xbaa7bb64,0xb872b9a8,0xb23eb61f,0xb23e0000,0xb872b61f,0xbaa7b9a8,0xbbd9bb64,
0xbb64bc00,0xb61fb9a8,0x361f0000,0x3b6439a8,0x3b643c00,0x361f39a8,0xb61f8000,0xbb64b9a8,0x361f0000,0x3b6439a8,0x3b643c00,0x361f39a8,0xb61f0000,0xbb64b9a8,0xbb64bc00,0xb61fb9a8,
};
__device__ __align__(1024) bf16 g_o[SEQ * DM];
__device__ __align__(1024) bf16 g_x1T[DM * XP];
__device__ __align__(1024) bf16 g_x2T[DM * XP];
__device__ __align__(1024) float2 g_sums[2][SEQ];

#define TSTAMP(slot, pt)
#define TSTAMP2(slot, i)

constexpr int KC_PITCH = 664, KC_MAX = 661;
__device__ __align__(1024) float g_kc[DM * KC_PITCH];
__device__ __forceinline__ int km_idx(int i) {
    if (i < 256) return (i & 7) * 36 + (i >> 3);
    if (i < 384) return (8 + (i & 3)) * 36 + ((i - 256) >> 2);
    if (i < 512) return (12 + 2 * ((i - 384) >> 6) + (i & 1)) * 36 + (((i - 384) & 63) >> 1);
    return (16 + ((i - 512) >> 5)) * 36 + (i & 31);
}

#define KSTAMP(i)
struct cplx { float r, i; };
__device__ __forceinline__ cplx cmul(cplx a, cplx b) {
    cplx o;
    o.r = fmaf(a.r, b.r, -a.i * b.i);
    o.i = fmaf(a.r, b.i, a.i * b.r);
    return o;
}
__device__ __forceinline__ cplx csq(cplx a) {
    cplx o;
    o.r = fmaf(a.r, a.r, -a.i * a.i);
    o.i = 2.f * a.r * a.i;
    return o;
}
__device__ __forceinline__ cplx cexp_p(float arl, float ai, float p) {
    float mag = ex2(arl * p);
    float ang = ai * p;
    float n = rintf(ang * 0.15915494309189535f);
    float r = fmaf(n, -6.2831854820251465f, ang);
    r = fmaf(n, 1.7484555e-7f, r);
    cplx o;
    o.r = mag * __cosf(r);
    o.i = mag * __sinf(r);
    return o;
}

__device__ __forceinline__ uint32_t pack2h(float lo, float hi) {
    uint32_t r;
    asm("cvt.rn.f16x2.f32 %0, %1, %2;" : "=r"(r) : "f"(hi), "f"(lo));
    return r;
}
__device__ __forceinline__ uint32_t cmul_h2(uint32_t a, uint32_t b1, uint32_t b2) {
    const __half2 av = *reinterpret_cast<const __half2*>(&a);
    const __half2 o = __hfma2(__high2half2(av), *reinterpret_cast<const __half2*>(&b2), __hmul2(__low2half2(av), *reinterpret_cast<const __half2*>(&b1)));
    return *reinterpret_cast<const uint32_t*>(&o);
}
__device__ __forceinline__ void mma16816_f16(float (&c)[4], uint32_t a0, uint32_t a1, uint32_t a2, uint32_t a3, uint32_t b0, uint32_t b1) {
    asm("mma.sync.aligned.m16n8k16.row.col.f32.f16.f16.f32 {%0,%1,%2,%3},{%4,%5,%6,%7},{%8,%9},{%0,%1,%2,%3};"
        : "+f"(c[0]), "+f"(c[1]), "+f"(c[2]), "+f"(c[3]) : "r"(a0), "r"(a1), "r"(a2), "r"(a3), "r"(b0), "r"(b1));
}
constexpr int KG_ROWB = 144;
constexpr int KG_WARPB = 56 * KG_ROWB;

struct SsmParams { const bf16 *lar, *aim, *cre, *cim, *logdt, *dskip; };
constexpr int KG_OUT = 12 * KG_WARPB;
constexpr int KG_SCRATCH = KG_OUT + 5 * KC_PITCH * 4;
constexpr int KG_KS = 3584;

__device__ __forceinline__ void kgen_cta(int d0, uint32_t scr, int tid, const SsmParams& sp) {
    const int warp = tid >> 5, lane = tid & 31;
    const int c = (warp < 8) ? warp >> 1 : 4;
    const int b0 = (warp < 8) ? 3 * (warp & 1) : (warp < 10) ? 2 * (warp - 8) : warp - 6;
    const int nb = (warp < 8) ? 3 : (warp < 10) ? 2 : 1;
    const int d = d0 + c;
    const uint32_t wb = scr + warp * KG_WARPB;
    KSTAMP(0);
    uint16_t pl[3], pa[3], pr[3], pi[3];
#pragma unroll
    for (int b = 0; b < 3; b++) {
        const int idx = d * NMODE + (b0 + min(b, nb - 1)) * 32 + lane;
        pl[b] = __ldg((const uint16_t*)sp.lar + idx); pa[b] = __ldg((const uint16_t*)sp.aim + idx);
        pr[b] = __ldg((const uint16_t*)sp.cre + idx); pi[b] = __ldg((const uint16_t*)sp.cim + idx);
    }
    const uint16_t pd = __ldg((const uint16_t*)sp.logdt + d);
    float dsk[5];
#pragma unroll
    for (int k = 0; k < 5; k++) dsk[k] = tid ? 0.f : __bfloat162float(sp.dskip[d0 + k]);
    if (tid < 5) sts32(scr + KG_OUT + (tid * KC_PITCH + KC_MAX) * 4, 0u);
#pragma unroll
    for (int h = 21; h < 24; h++) sts32(wb + (32 + h) * KG_ROWB + lane * 4, 0u);
    auto B = [](uint16_t v) { return __uint_as_float((uint32_t)v << 16); };
    const float dt = rbf(ex2(B(pd) * 1.4426950408889634f));
    float cm = 0.f;
#pragma unroll
    for (int b = 0; b < 3; b++) cm = fmaxf(cm, fmaxf(fabsf(B(pr[b])), fabsf(B(pi[b]))));
    const uint32_t e = min(max(__reduce_max_sync(~0u, __float_as_uint(2.f * dt * cm)) >> 23, 2u), 252u);
    const float cscale = __uint_as_float((253u - e) << 23), cinv = __uint_as_float((e + 1u) << 23);
    KSTAMP(1);
    float acc[2][3][4];
#pragma unroll
    for (int m = 0; m < 2; m++)
#pragma unroll
        for (int n = 0; n < 3; n++) acc[m][n][0] = acc[m][n][1] = acc[m][n][2] = acc[m][n][3] = 0.f;
#pragma unroll 1
    for (int b = 0; b < nb; b++) {
        const float plar = B(b == 0 ? pl[0] : b == 1 ? pl[1] : pl[2]), pai = B(b == 0 ? pa[0] : b == 1 ? pa[1] : pa[2]);
        const float pcr = B(b == 0 ? pr[0] : b == 1 ? pr[1] : pr[2]), pci = B(b == 0 ? pi[0] : b == 1 ? pi[1] : pi[2]);
        const float Ar = -rbf(ex2(plar * 1.4426950408889634f));
        const float arl = Ar * dt * 1.4426950408889634f;
        const float ai = pai * dt;
        const uint32_t wa = wb + lane * 4;
        {
            const cplx B1 = cexp_p(arl, ai, 8.f), B2 = csq(B1), B3 = cmul(B2, B1), B4 = csq(B2), B5 = cmul(B4, B1), B6 = csq(B3), B7 = cmul(B4, B3);
            const cplx A1 = csq(B4), A2 = csq(A1), A3 = cmul(A2, A1);
            const uint32_t bj[8] = {0x00003C00u, pack2h(B1.r, B1.i), pack2h(B2.r, B2.i), pack2h(B3.r, B3.i),
                                    pack2h(B4.r, B4.i), pack2h(B5.r, B5.i), pack2h(B6.r, B6.i), pack2h(B7.r, B7.i)};
            const uint32_t a1[3] = {pack2h(A1.r, A1.i), pack2h(A2.r, A2.i), pack2h(A3.r, A3.i)};
            const uint32_t a2[3] = {pack2h(-A1.i, A1.r), pack2h(-A2.i, A2.r), pack2h(-A3.i, A3.r)};
#pragma unroll
            for (int j = 0; j < 8; j++) {
                sts32(wa + j * KG_ROWB, bj[j]);
#pragma unroll
                for (int i = 0; i < 3; i++) sts32(wa + (8 * (i + 1) + j) * KG_ROWB, j ? cmul_h2(bj[j], a1[i], a2[i]) : a1[i]);
            }
        }
        {
            const uint32_t wh = wa + 32 * KG_ROWB;
            cplx z1 = cexp_p(arl, -ai, 1.f), z2 = csq(z1), z4 = csq(z2), z256 = cexp_p(arl, -ai, 256.f);
            cplx H0 = {2.f * pcr * dt * cscale, -2.f * pci * dt * cscale};
            cplx E = H0, O = cmul(H0, z1);
#pragma unroll
            for (int h = 0; h < 8; h += 2) {
                sts32(wh + (h + 0) * KG_ROWB, pack2h(E.r, E.i));
                sts32(wh + (h + 1) * KG_ROWB, pack2h(O.r, O.i));
                if (h < 6) { E = cmul(E, z2); O = cmul(O, z2); }
            }
            cplx G = cmul(H0, z256);
            cplx G2 = cmul(G, z2), G4 = cmul(G, z4), G6 = cmul(G2, z4);
            sts32(wh + 8 * KG_ROWB, pack2h(G.r, G.i));
            sts32(wh + 9 * KG_ROWB, pack2h(G2.r, G2.i));
            sts32(wh + 10 * KG_ROWB, pack2h(G4.r, G4.i));
            sts32(wh + 11 * KG_ROWB, pack2h(G6.r, G6.i));
            G = cmul(G, z256);
            G4 = cmul(G, z4);
            sts32(wh + 12 * KG_ROWB, pack2h(G.r, G.i));
            sts32(wh + 13 * KG_ROWB, pack2h(G4.r, G4.i));
            G = cmul(G, z256);
            G4 = cmul(G, z4);
            sts32(wh + 14 * KG_ROWB, pack2h(G.r, G.i));
            sts32(wh + 15 * KG_ROWB, pack2h(G4.r, G4.i));
#pragma unroll
            for (int h = 16; h < 21; h++) {
                G = cmul(G, z256);
                sts32(wh + h * KG_ROWB, pack2h(G.r, G.i));
            }
        }
        __syncwarp();
        const int mi = lane >> 3, mr = lane & 7;
#pragma unroll
        for (int kp = 0; kp < 2; kp++) {
            uint32_t bq[3][4];
#pragma unroll
            for (int nt = 0; nt < 3; nt++)
                ldsm_x4(bq[nt][0], bq[nt][1], bq[nt][2], bq[nt][3], wb + (32 + 8 * nt + mr) * KG_ROWB + kp * 64 + mi * 16);
#pragma unroll
            for (int kk = 0; kk < 2; kk++) {
#pragma unroll
                for (int mt = 0; mt < 2; mt++) {
                    uint32_t a0, a1, a2, a3;
                    ldsm_x4(a0, a1, a2, a3, wb + (16 * mt + (mi & 1) * 8 + mr) * KG_ROWB + (kp * 2 + kk) * 32 + (mi >> 1) * 16);
#pragma unroll
                    for (int nt = 0; nt < 3; nt++) mma16816_f16(acc[mt][nt], a0, a1, a2, a3, bq[nt][kk * 2], bq[nt][kk * 2 + 1]);
                }
            }
        }
        __syncwarp();
        KSTAMP(2 + b);
    }
    {
        const int g = lane >> 2, q = lane & 3;
#pragma unroll
        for (int mt = 0; mt < 2; mt++)
#pragma unroll
            for (int nt = 0; nt < 3; nt++) {
                const uint32_t o = wb + ((8 * nt + 2 * q) * 36 + 16 * mt + g) * 4;
                sts32(o, __float_as_uint(acc[mt][nt][0] * cinv)); sts32(o + 36 * 4, __float_as_uint(acc[mt][nt][1] * cinv));
                sts32(o + 8 * 4, __float_as_uint(acc[mt][nt][2] * cinv)); sts32(o + 44 * 4, __float_as_uint(acc[mt][nt][3] * cinv));
            }
    }
    KSTAMP(5);
    __syncthreads();
    KSTAMP(6);
    {
        auto F = [](uint32_t x) { return __uint_as_float(x); };
        auto add4 = [&](uint4 a, uint4 b) {
            return make_uint4(__float_as_uint(F(a.x) + F(b.x)), __float_as_uint(F(a.y) + F(b.y)), __float_as_uint(F(a.z) + F(b.z)), __float_as_uint(F(a.w) + F(b.w)));
        };
        uint4 v[3];
#pragma unroll
        for (int k = 0; k < 3; k++) {
            const int i = tid + 384 * k, ch = min(i / 216, 4), o = i - ch * 216;
            const uint32_t a = scr + 2 * ch * KG_WARPB + min(o, 215) * 16;
            v[k] = add4(lds128(a), lds128(a + KG_WARPB));
            if (ch == 4) v[k] = add4(v[k], add4(lds128(a + 2 * KG_WARPB), lds128(a + 3 * KG_WARPB)));
        }
#pragma unroll
        for (int k = 0; k < 3; k++) {
            const int i = tid + 384 * k, ch = min(i / 216, 4), o = i - ch * 216;
            if (i < 1080) sts128(scr + KG_KS + ch * KG_WARPB + o * 16, v[k]);
        }
        if (tid < 5) sts128(scr + KG_KS + tid * KG_WARPB + 864 * 4, make_uint4(0, 0, 0, 0));
    }
    KSTAMP(7);
    __syncthreads();
    KSTAMP(8);
    {
        const int i1 = min(tid + 384, 640);
        const uint32_t s0 = scr + KG_KS + km_idx(tid) * 4, s1 = scr + KG_KS + km_idx(i1) * 4;
        float v0[5], v1[5];
#pragma unroll
        for (int ch = 0; ch < 5; ch++) { v0[ch] = __uint_as_float(lds32(s0 + ch * KG_WARPB)) + dsk[ch]; v1[ch] = __uint_as_float(lds32(s1 + ch * KG_WARPB)); }
#pragma unroll
        for (int ch = 0; ch < 5; ch++) {
            sts32(scr + KG_OUT + (ch * KC_PITCH + tid + (tid >> 5)) * 4, __float_as_uint(v0[ch]));
            sts32(scr + KG_OUT + (ch * KC_PITCH + i1 + (i1 >> 5)) * 4, __float_as_uint(v1[ch]));
            const uint32_t m = __reduce_max_sync(~0u, __float_as_uint(fmaxf(fabsf(v0[ch]), fabsf(v1[ch]))));
            if (lane == 0) asm volatile("red.shared.max.u32 [%0], %1;" ::"r"(scr + KG_OUT + (ch * KC_PITCH + KC_MAX) * 4), "r"(m) : "memory");
        }
    }
    fence_async_smem();
    __syncthreads();
    if (tid == 0) {
        asm volatile("cp.async.bulk.global.shared::cta.bulk_group [%0], [%1], %2;" ::"l"(g_kc + d0 * KC_PITCH), "r"(scr + KG_OUT), "r"(5 * KC_PITCH * 4) : "memory");
        asm volatile("cp.async.bulk.commit_group;" ::: "memory");
    }
    KSTAMP(9);
}
#define Q_SCHED 0
#define Q_WAITFOR(it) (Q_SCHED == 0 ? (it) - 2 : Q_SCHED == 1 ? ((it) == 3 ? 1 : 0) : Q_SCHED == 2 ? 0 : (it) - 1)
#define Q_DELAY_STATS 1
constexpr int Q_ST = 4;
constexpr int Q_AB = 16384, Q_BB = 30720, Q_SB = Q_AB + Q_BB;
constexpr int Q_EROW = 336;
constexpr int Q_ESLOT = 8 * Q_EROW;
constexpr int Q_OROW = 176;
constexpr int Q_EOFF = Q_ST * Q_SB;
#define O_COMBINE 1
constexpr int O_ST = 4;
constexpr int O_AB = 8192, O_BB = 20480;
constexpr int O_ROFF = 0;
constexpr int O_AOFF = 24576, O_BOFF = O_AOFF + 10 * O_AB;
constexpr int O_TROW = 176;
static_assert(O_BOFF + O_ST * O_BB <= Q_ST * Q_SB && 8 * 16 * Q_OROW <= O_AOFF, "phase W layout");
constexpr int Q_KG = 2 * Q_SB;
constexpr int Q_SMEM = (Q_EOFF + 8 * Q_ESLOT > Q_KG + KG_SCRATCH ? Q_EOFF + 8 * Q_ESLOT : Q_KG + KG_SCRATCH) + 1024;

__device__ unsigned g_epoch;
__device__ __align__(1024) unsigned long long g_stats[2][SEQ];
__device__ __align__(1024) unsigned long long g_csp[8][16][240];
__device__ __align__(1024) float g_colsum[3 * DM];
__device__ __align__(128) unsigned g_oflag[2][16][8];
__device__ __align__(1024) unsigned long long g_halo[128][20][32];

__device__ __forceinline__ unsigned long long ld_ll(const unsigned long long* p) {
    unsigned long long v;
    asm volatile("ld.relaxed.gpu.global.b64 %0, [%1];" : "=l"(v) : "l"(p) : "memory");
    return v;
}
__device__ __forceinline__ uint32_t wait_ll(const unsigned long long* p, unsigned long long v, uint32_t tag) {
    int n = 0;
    while ((uint32_t)(v >> 32) != tag && ++n < (1 << 20)) v = ld_ll(p);
    return (uint32_t)v;
}
__device__ __forceinline__ void st_ll(unsigned long long* p, uint32_t payload, uint32_t tag) {
    const unsigned long long v = (unsigned long long)payload | ((unsigned long long)tag << 32);
    asm volatile("st.relaxed.gpu.global.b64 [%0], %1;" ::"l"(p), "l"(v) : "memory");
}
__device__ __forceinline__ float2 unpack_stats(uint32_t v) { return make_float2(bf_hi(v), frcp(bf_lo(v))); }

__global__ void __launch_bounds__(384, 1)
attn_kernel(const __grid_constant__ CUtensorMap mX, const __grid_constant__ CUtensorMap mW, const __grid_constant__ CUtensorMap mWr,
            const __grid_constant__ CUtensorMap mWo, const __grid_constant__ CUtensorMap mO, const __grid_constant__ CUtensorMap mRes,
            const bf16* __restrict__ xin, const bf16* __restrict__ wqkv, const bf16* __restrict__ wo, bf16* __restrict__ outT,
            float2* __restrict__ sums, const SsmParams sp, int layer, int slot) {
    extern __shared__ __align__(1024) char smraw[];
    __shared__ __align__(8) uint64_t s_full[Q_ST], s_empty[Q_ST];
    __shared__ __align__(8) uint64_t s_ofull[O_ST], s_oempty[O_ST], s_wfull, s_res, s_free, s_qdone, s_odone;
    __shared__ __align__(16) float s_cs[240];
    __shared__ float s_red[3][16][2];
    const uint32_t sb = (s2u(smraw) + 1023) & ~1023u;
    const int tid = threadIdx.x, warp = __shfl_sync(~0u, tid >> 5, 0), lane = tid & 31;
    const int par = blockIdx.x & 1, cl = blockIdx.x >> 1, R = cl & 7, hg = cl >> 3;
    const int r0 = par * 1024 + R * 128;
    const bool has_q = blockIdx.x < 128;
    const int w_r0 = (cl % 13) * 160, w_c0 = (2 * (cl / 13) + par) * 64;
    const int g = lane >> 2, q = lane & 3;
    if (tid == 0) TSTAMP(slot, 0);
    if (tid == 256) { prefetch_tmap(&mW); prefetch_tmap(&mWr); prefetch_tmap(&mX); prefetch_tmap(&mWo); prefetch_tmap(&mO); prefetch_tmap(&mRes); }
    if (tid == 0) {
        for (int i = 0; i < Q_ST; i++) { mbar_init(s2u(&s_full[i]), 1); mbar_init(s2u(&s_empty[i]), 16); }
        for (int i = 0; i < O_ST; i++) { mbar_init(s2u(&s_ofull[i]), 1); mbar_init(s2u(&s_oempty[i]), 4); }
        mbar_init(s2u(&s_wfull), 1); mbar_init(s2u(&s_res), 1); mbar_init(s2u(&s_free), 2); mbar_init(s2u(&s_qdone), 1); mbar_init(s2u(&s_odone), 1);
        fence_mbar_init();
    }
    __syncthreads();
    cluster_arrive_relaxed();
    cluster_wait();

    auto issue_w = [&](int it) {
        const int s = it & (Q_ST - 1);
        const uint32_t fb = s2u(&s_full[s]), db = sb + s * Q_SB + Q_AB + par * 15360;
        const int k0 = it * 64 + par * 32;
#pragma unroll
        for (int p = 0; p < 3; p++) tma2d_mc(db + p * 4096, &mW, p * DM + hg * 80, k0, fb, 3);
        tma3d_mc(db + 12288, &mWr, hg * 80 + 64, k0, 0, fb, 3);
    };
    if (layer == 0 && has_q) {
        if (warp == 8) {
            if (elect_one()) {
#pragma unroll 1
                for (int it = 0; it < 2; it++) {
                    mbar_expect(s2u(&s_full[it]), Q_SB);
                    tma3d(sb + it * Q_SB, &mX, it * 64, par, R * 128, s2u(&s_full[it]));
                    issue_w(it);
                }
            }
            __syncwarp();
        }
        if (tid < 50) asm volatile("prefetch.global.L2 [%0];" ::"l"((const char*)wo + (size_t)(blockIdx.x * 50 + tid) * 128));
        if (tid >= 64 && tid < 67 && blockIdx.x * 3 + tid - 64 < sizeof(c_fft) / 128) asm volatile("prefetch.global.L2 [%0];" ::"l"((const char*)c_fft + (size_t)(blockIdx.x * 3 + tid - 64) * 128));
        if (warp >= 10) {
            const uint32_t tag = 2u * g_epoch + 1u;
            const int j = 2 * R + par;
#pragma unroll 1
            for (int p = tid - 320; p < 120; p += 64) {
                const bf16* src = wqkv + (size_t)(40 * j) * (3 * DM) + (p / 40) * DM + hg * 80 + 2 * (p % 40);
                float s0 = 0.f, s1 = 0.f;
#pragma unroll 1
                for (int i0 = 0; i0 < 40; i0 += 20) {
                    uint32_t v[20];
#pragma unroll
                    for (int i = 0; i < 20; i++) v[i] = __ldg((const uint32_t*)(src + (size_t)(i0 + i) * (3 * DM)));
#pragma unroll
                    for (int i = 0; i < 20; i++) { s0 += bf_lo(v[i]); s1 += bf_hi(v[i]); }
                }
                st_ll(&g_csp[hg][j][2 * p], __float_as_uint(s0), tag);
                st_ll(&g_csp[hg][j][2 * p + 1], __float_as_uint(s1), tag);
            }
        }
        kgen_cta(blockIdx.x * 5, sb + Q_KG, tid, sp);
        fence_async_smem();
        cluster_arrive_relaxed();
        if (tid == 0) TSTAMP(slot, 2);
    }

    if (warp >= 8) {
        asm volatile("setmaxnreg.dec.sync.aligned.u32 56;");
        if (layer == 0 && has_q) cluster_wait();
        if (warp == 8 && has_q && elect_one()) {
            if (layer) {
                mbar_expect(s2u(&s_full[0]), Q_SB);
                issue_w(0);
                pdl_wait();
            }
#pragma unroll 1
            for (int it = layer ? 0 : 2; it < 10; it++) {
                const int s = it & (Q_ST - 1);
                const uint32_t d = sb + s * Q_SB, fb = s2u(&s_full[s]);
                if (it >= Q_ST) mbar_wait(s2u(&s_empty[s]), ((it >> 2) - 1) & 1);
                else if (it > 0 && Q_WAITFOR(it) >= 0) mbar_wait(s2u(&s_full[Q_WAITFOR(it)]), 0);
                if (it > 0) mbar_expect(fb, Q_SB);
                if (layer == 0) {
                    tma3d(d, &mX, it * 64, par, R * 128, fb);
                } else {
                    tma2d(d, &mX, r0, it * 64, fb);
                    tma2d(d + 8192, &mX, r0 + 64, it * 64, fb);
                }
                if (it > 0) issue_w(it);
            }
        }
        if (warp == 8) {
            __syncwarp();
            const uint32_t tag = 2u * g_epoch + layer + 1u;
            pdl_wait();
            if (has_q) mbar_wait(s2u(&s_qdone), 0);
            if (elect_one()) {
                mbar_expect(s2u(&s_wfull), 10 * O_AB);
#pragma unroll 1
                for (int it = 0; it < 10; it++) tma2d(sb + O_AOFF + it * O_AB, &mWo, w_c0, it * 64, s2u(&s_wfull));
            }
            __syncwarp();
            if (has_q) mbar_wait(s2u(&s_odone), 0);
            if (elect_one()) {
                if (layer == 0) {
                    const int nb = min(5, (SEQ - w_r0) / 32);
                    mbar_expect(s2u(&s_res), nb * 4096);
                    for (int b = 0; b < nb; b++) { const int r = w_r0 + 32 * b; tma3d(sb + O_ROFF + b * 4096, &mRes, w_c0, r >> 10, r & 1023, s2u(&s_res)); }
                } else {
                    mbar_expect(s2u(&s_res), 3 * 8192);
                    for (int b = 0; b < 3; b++) tma2d(sb + O_ROFF + b * 8192, &mRes, w_r0 + 64 * b, w_c0, s2u(&s_res));
                }
            }
            if (lane < 16) {
                const unsigned* fp = &g_oflag[layer][min(15, (w_r0 + (lane >> 3) * 159) >> 7)][lane & 7];
                unsigned v;
                int spin = 0;
                do { asm volatile("ld.acquire.gpu.global.u32 %0, [%1];" : "=r"(v) : "l"(fp) : "memory"); } while (v != tag && ++spin < (1 << 20));
            }
            __syncwarp();
            asm volatile("fence.proxy.async;" ::: "memory");
            mbar_wait(s2u(&s_free), 0);
            if (elect_one()) {
#pragma unroll 1
                for (int it = 0; it < 10; it++) {
                    const int s = it & (O_ST - 1);
                    if (it >= O_ST) mbar_wait(s2u(&s_oempty[s]), ((it >> 2) - 1) & 1);
                    mbar_expect(s2u(&s_ofull[s]), O_BB);
                    tma2d_mc(sb + O_BOFF + s * O_BB + par * 10240, &mO, it * 64, w_r0 + par * 80, s2u(&s_ofull[s]), 3);
                }
            }
        }
        if (warp > 8 && has_q) {
            const int ht = tid - 288, hw = warp - 9, mi = lane >> 3, mj = lane & 7;
            pdl_wait();
            const uint32_t tag = 2u * g_epoch + layer + 1u;
            mbar_wait(s2u(&s_full[1]), 0);
            if (layer == 0) {
#pragma unroll 1
                for (int i0 = 2 * hw; i0 < 16; i0 += 6) {
                    uint32_t v[2][10];
#pragma unroll
                    for (int h = 0; h < 2; h++) {
                        const bf16* src = xin + (size_t)(2 * (R * 128 + 16 * hg + i0 + h) + par) * DM + 2 * lane;
#pragma unroll
                        for (int j = 0; j < 10; j++) v[h][j] = __ldg((const uint32_t*)(src + 64 * j));
                    }
#pragma unroll
                    for (int h = 0; h < 2; h++) {
                        float a = 0.f, b = 0.f;
#pragma unroll
                        for (int j = 0; j < 10; j++) {
                            const float lo = bf_lo(v[h][j]), hi = bf_hi(v[h][j]);
                            a += lo + hi; b = fmaf(lo, lo, fmaf(hi, hi, b));
                        }
#pragma unroll
                        for (int o = 1; o <= 16; o <<= 1) { a += __shfl_xor_sync(~0u, a, o); b += __shfl_xor_sync(~0u, b, o); }
                        if (lane == 0) {
                            s_red[0][i0 + h][0] = a; s_red[0][i0 + h][1] = b;
                            s_red[1][i0 + h][0] = s_red[1][i0 + h][1] = s_red[2][i0 + h][0] = s_red[2][i0 + h][1] = 0.f;
                        }
                    }
                }
            } else {
                float a0 = 0.f, a1 = 0.f, b0 = 0.f, b1 = 0.f;
                const bf16* src = xin + (size_t)(4 * hw + mi) * XP + r0 + 16 * hg + 2 * mj;
#pragma unroll 1
                for (int i0 = 0; i0 < 54; i0 += 18) {
                    uint32_t v[18];
#pragma unroll
                    for (int i = 0; i < 18; i++) v[i] = (12 * (i0 + i) + 4 * hw + mi < DM) ? __ldg((const uint32_t*)(src + (size_t)12 * (i0 + i) * XP)) : 0u;
#pragma unroll
                    for (int i = 0; i < 18; i++) {
                        const float lo = bf_lo(v[i]), hi = bf_hi(v[i]);
                        a0 += lo; b0 = fmaf(lo, lo, b0); a1 += hi; b1 = fmaf(hi, hi, b1);
                    }
                }
#pragma unroll
                for (int o = 8; o <= 16; o <<= 1) {
                    a0 += __shfl_xor_sync(~0u, a0, o); b0 += __shfl_xor_sync(~0u, b0, o);
                    a1 += __shfl_xor_sync(~0u, a1, o); b1 += __shfl_xor_sync(~0u, b1, o);
                }
                if (mi == 0) {
                    s_red[hw][2 * mj][0] = a0; s_red[hw][2 * mj][1] = b0;
                    s_red[hw][2 * mj + 1][0] = a1; s_red[hw][2 * mj + 1][1] = b1;
                }
            }
            named_bar(4, 96);
            if (ht < 16) {
                const float sm = s_red[0][ht][0] + s_red[1][ht][0] + s_red[2][ht][0], sq = s_red[0][ht][1] + s_red[1][ht][1] + s_red[2][ht][1];
                st_ll(g_stats[layer] + r0 + 16 * hg + ht, ln_finish_packed(sm, sq), tag);
                sums[r0 + 16 * hg + ht] = make_float2(0.f, 0.f);
            }
#pragma unroll 1
            for (int c = ht; c < 240; c += 96) {
                const int ci = (c / 80) * DM + hg * 80 + c % 80;
                float v = 0.f;
                if (layer == 0) {
                    unsigned long long w[16];
                    int spin = 0;
                    bool ok;
                    do {
                        ok = true;
#pragma unroll
                        for (int j = 0; j < 16; j++) w[j] = ld_ll(&g_csp[hg][j][c]);
#pragma unroll
                        for (int j = 0; j < 16; j++) ok = ok && ((uint32_t)(w[j] >> 32) == tag);
                    } while (!ok && ++spin < (1 << 18));
#pragma unroll
                    for (int j = 0; j < 16; j++) v += __uint_as_float((uint32_t)w[j]);
                    if (R == 0 && par == 0) g_colsum[ci] = v;
                } else {
                    v = g_colsum[ci];
                }
                s_cs[c] = v;
            }
            asm volatile("bar.arrive 3, 352;" ::: "memory");
        }
        __syncwarp();
        cluster_arrive_relaxed();
        cluster_wait();
    } else {
    asm volatile("setmaxnreg.inc.sync.aligned.u32 224;");
    pdl_wait();
    if (layer || !has_q) pdl_launch();
    if (tid == 0) TSTAMP(slot, 1);
    const int wg = warp >> 2;
    const int mi = lane >> 3, mj = lane & 7;
    if (has_q) {
    uint32_t epoch;
    asm volatile("ld.global.u32 %0, [%1];" : "=r"(epoch) : "l"(&g_epoch));
    unsigned long long* stats = g_stats[layer];
    float acc[120];
    auto stage = [&](int it) {
        const int s = it & (Q_ST - 1);
        const uint32_t st = sb + s * Q_SB;
        mbar_wait(s2u(&s_full[s]), (it >> 2) & 1);
        const uint64_t da = mkdesc(st + wg * 8192, 16, 1024, 1);
        const uint64_t db = mkdesc(st + Q_AB, 4096, 1024, 1);
        const uint64_t dr = mkdesc(st + Q_AB + 12288, 1024, 256, 3);
        wg_fence();
        if (layer == 0) {
#pragma unroll
            for (int ks = 0; ks < 4; ks++) {
                const int sc = (ks > 0) ? 1 : (it > 0);
                wgmma_n192<0, 1>(*(float(*)[96]) & acc[0], da + ks * 2, db + (ks >> 1) * 960 + (ks & 1) * 128, sc);
                wgmma_n48<0, 1>(*(float(*)[24]) & acc[96], da + ks * 2, dr + (ks >> 1) * 960 + (ks & 1) * 32, sc);
            }
            wg_commit();
        } else {
#pragma unroll
            for (int ks = 0; ks < 4; ks++) {
                const int sc = (ks > 0) ? 1 : (it > 0);
                wgmma_n192<1, 1>(*(float(*)[96]) & acc[0], da + ks * 128, db + (ks >> 1) * 960 + (ks & 1) * 128, sc);
                wgmma_n48<1, 1>(*(float(*)[24]) & acc[96], da + ks * 128, dr + (ks >> 1) * 960 + (ks & 1) * 32, sc);
            }
            wg_commit();
        }
        wg_wait<1>();
        if (it > 0 && it <= 10 - Q_ST && lane == 0) {
            mbar_arrive_cta(s2u(&s_empty[(it - 1) & (Q_ST - 1)]), 0);
            mbar_arrive_cta(s2u(&s_empty[(it - 1) & (Q_ST - 1)]), 1);
        }
    };
#pragma unroll 1
    for (int it = 0; it < 10; it++) {
        stage(it);
        if (it == 0 && tid == 0) TSTAMP(slot, 3);
    }
    const uint32_t tag = 2u * epoch + layer + 1u;
    const int row = r0 + 16 * warp + g;
    const bool first = (R == 0 && warp == 0);
    const unsigned long long* pp = stats + (first ? row : r0 + 16 * warp - 8 + 2 * q);
    const unsigned long long sr0 = ld_ll(stats + row), sr1 = ld_ll(stats + row + 8), sp0 = ld_ll(pp), sp1 = ld_ll(pp + 1);
    wg_wait<0>();
    if (tid == 0) TSTAMP(slot, 4);
    if (layer == 0) {
        cluster_wait();
        if (tid == 0) {
            asm volatile("cp.async.bulk.wait_group 0;" ::: "memory");
            pdl_launch();
        }
    }
    named_bar(3, 352);
    const float2 s0 = unpack_stats(wait_ll(stats + row, sr0, tag)), s1 = unpack_stats(wait_ll(stats + row + 8, sr1, tag));
    const float rp0 = unpack_stats(wait_ll(pp, sp0, tag)).y, rp1 = unpack_stats(wait_ll(pp + 1, sp1, tag)).y;
    uint32_t ql[10], qh[10], kl[10], kh[10], vl[10], vh[10];
    auto fold = [&](int p, int f, uint32_t& lo, uint32_t& hi) {
        const int j = (f < 8) ? 8 * p + f : 24 + 2 * p + (f - 8);
        const float2 c = *(const float2*)&s_cs[p * 80 + 8 * f + 2 * q];
        lo = pack2(fmaf(-s0.x, c.x, acc[4 * j]), fmaf(-s0.x, c.y, acc[4 * j + 1]));
        hi = pack2(fmaf(-s1.x, c.x, acc[4 * j + 2]), fmaf(-s1.x, c.y, acc[4 * j + 3]));
    };
#pragma unroll
    for (int f = 0; f < 10; f++) { fold(1, f, kl[f], kh[f]); fold(2, f, vl[f], vh[f]); }
    if (warp == 7 && R < 7) {
        unsigned long long* hp = &g_halo[blockIdx.x][0][lane];
#pragma unroll
        for (int f = 0; f < 10; f++) { st_ll(hp + 32 * f, kh[f], tag); st_ll(hp + 32 * (10 + f), vh[f], tag); }
    }
    if (warp < 7) {
        const uint32_t a = sb + Q_EOFF + (warp + 1) * Q_ESLOT + mj * Q_EROW + mi * 16;
        stsm_x4(a, kh[0], kh[1], kh[2], kh[3]);
        stsm_x4(a + 64, kh[4], kh[5], kh[6], kh[7]);
        stsm_x4(a + 128, kh[8], kh[9], vh[0], vh[1]);
        stsm_x4(a + 192, vh[2], vh[3], vh[4], vh[5]);
        stsm_x4(a + 256, vh[6], vh[7], vh[8], vh[9]);
    }
#pragma unroll
    for (int f = 0; f < 10; f++) fold(0, f, ql[f], qh[f]);
    uint32_t vt1[10], vt2[10];
#pragma unroll
    for (int f = 0; f < 10; f++) { vt1[f] = movm_t(vl[f]); vt2[f] = movm_t(vh[f]); }
    named_bar(1, 256);
    if (tid == 0) { mbar_arrive(s2u(&s_qdone)); mbar_arrive_cta(s2u(&s_free), 0); mbar_arrive_cta(s2u(&s_free), 1); }
    if (tid == 0) TSTAMP(slot, 5);
    uint32_t kp[10], vp[10];
    if (warp > 0) {
        const uint32_t a = sb + Q_EOFF + warp * Q_ESLOT + mj * Q_EROW + mi * 16;
        ldsm_x4(kp[0], kp[1], kp[2], kp[3], a);
        ldsm_x4(kp[4], kp[5], kp[6], kp[7], a + 64);
        ldsm_x2(kp[8], kp[9], a + 128);
        ldsm_x4_t(vp[0], vp[1], vp[2], vp[3], a + 160);
        ldsm_x4_t(vp[4], vp[5], vp[6], vp[7], a + 224);
        ldsm_x2_t(vp[8], vp[9], a + 288 - (lane >> 4) * 32);
    } else if (R > 0) {
        const unsigned long long* hp = &g_halo[blockIdx.x - 2][0][lane];
        unsigned long long hv[20];
        int spin = 0;
        bool ok;
        do {
            ok = true;
#pragma unroll
            for (int f = 0; f < 20; f++) hv[f] = ld_ll(hp + 32 * f);
#pragma unroll
            for (int f = 0; f < 20; f++) ok = ok && ((uint32_t)(hv[f] >> 32) == tag);
        } while (!__all_sync(~0u, ok) && ++spin < (1 << 18));
#pragma unroll
        for (int f = 0; f < 10; f++) { kp[f] = (uint32_t)hv[f]; vp[f] = movm_t((uint32_t)hv[10 + f]); }
    } else {
#pragma unroll
        for (int f = 0; f < 10; f++) { kp[f] = 0u; vp[f] = 0u; }
    }
    const bool sel0 = (2 * q > g), sel1 = (2 * q + 1 > g);
    constexpr float SC = 0.22360679774997896f * 1.4426950408889634f;
    const float ra0 = __shfl_sync(~0u, s0.y, 8 * q), ra1 = __shfl_sync(~0u, s0.y, 8 * q + 4);
    const float rb0 = __shfl_sync(~0u, s1.y, 8 * q), rb1 = __shfl_sync(~0u, s1.y, 8 * q + 4);
    const float kx0 = sel0 ? rp0 : ra0, kx1 = sel1 ? rp1 : ra1, ky0 = sel0 ? ra0 : rb0, ky1 = sel1 ? ra1 : rb1;
    const float cx0 = SC * s0.y * kx0, cx1 = SC * s0.y * kx1, cy0 = SC * s1.y * ky0, cy1 = SC * s1.y * ky1;
    float oacc[10][4];
#pragma unroll
    for (int h = 0; h < 4; h++) {
        const int fa = (h == 0) ? 0 : (h == 1) ? 3 : (h == 2) ? 5 : 8, fb = fa + 1, fh = (h < 2) ? 2 : 7;
        const bool mine = (h & 1) ? (q >= 2) : (q < 2);
        const uint32_t qml = mine ? ql[fh] : 0u, qmh = mine ? qh[fh] : 0u;
        float S0[4] = {0.f, 0.f, 0.f, 0.f}, S1[4] = {0.f, 0.f, 0.f, 0.f}, S2[4] = {0.f, 0.f, 0.f, 0.f};
        mma16816(S0, ql[fa], qh[fa], ql[fb], qh[fb], kp[fa], kp[fb]); mma1688(S0, qml, qmh, kp[fh]);
        mma16816(S1, ql[fa], qh[fa], ql[fb], qh[fb], kl[fa], kl[fb]); mma1688(S1, qml, qmh, kl[fh]);
        mma16816(S2, ql[fa], qh[fa], ql[fb], qh[fb], kh[fa], kh[fb]); mma1688(S2, qml, qmh, kh[fh]);
        float x0 = (sel0 ? S0[0] : S1[0]) * cx0, x1 = (sel1 ? S0[1] : S1[1]) * cx1;
        float y0 = (sel0 ? S1[2] : S2[2]) * cy0, y1 = (sel1 ? S1[3] : S2[3]) * cy1;
        if (first) { if (sel0) x0 = -INFINITY; if (sel1) x1 = -INFINITY; }
        float mx = fmaxf(x0, x1), my = fmaxf(y0, y1);
        mx = fmaxf(mx, __shfl_xor_sync(~0u, mx, 1)); my = fmaxf(my, __shfl_xor_sync(~0u, my, 1));
        mx = fmaxf(mx, __shfl_xor_sync(~0u, mx, 2)); my = fmaxf(my, __shfl_xor_sync(~0u, my, 2));
        x0 = ex2(x0 - mx); x1 = ex2(x1 - mx); y0 = ex2(y0 - my); y1 = ex2(y1 - my);
        float sx = x0 + x1, sy = y0 + y1;
        sx += __shfl_xor_sync(~0u, sx, 1); sy += __shfl_xor_sync(~0u, sy, 1);
        sx += __shfl_xor_sync(~0u, sx, 2); sy += __shfl_xor_sync(~0u, sy, 2);
        const float ix = frcp(sx), iy = frcp(sy);
        x0 *= ix * kx0; x1 *= ix * kx1; y0 *= iy * ky0; y1 *= iy * ky1;
        const uint32_t pa0 = pack2(sel0 ? x0 : 0.f, sel1 ? x1 : 0.f);
        const uint32_t pa2 = pack2(sel0 ? 0.f : x0, sel1 ? 0.f : x1);
        const uint32_t pa3 = pack2(sel0 ? y0 : 0.f, sel1 ? y1 : 0.f);
        const uint32_t pb1 = pack2(sel0 ? 0.f : y0, sel1 ? 0.f : y1);
#pragma unroll
        for (int i = 0; i < 3; i++) {
            const int f = (i == 0) ? fa : (i == 1) ? fb : fh;
            float O[4] = {0.f, 0.f, 0.f, 0.f};
            mma16816(O, pa0, 0u, pa2, pa3, vp[f], vt1[f]);
            mma1688(O, 0u, pb1, vt2[f]);
            if (i < 2 || !(h & 1) || mine) { oacc[f][0] = O[0]; oacc[f][1] = O[1]; oacc[f][2] = O[2]; oacc[f][3] = O[3]; }
        }
    }
    const uint32_t ob = sb + warp * 16 * Q_OROW;
    {
        const uint32_t a = ob + ((mi & 1) * 8 + mj) * Q_OROW + (mi >> 1) * 16;
#pragma unroll
        for (int f = 0; f < 10; f += 2)
            stsm_x4(a + f * 16, pack2(oacc[f][0], oacc[f][1]), pack2(oacc[f][2], oacc[f][3]),
                    pack2(oacc[f + 1][0], oacc[f + 1][1]), pack2(oacc[f + 1][2], oacc[f + 1][3]));
    }
    __syncwarp();
    bf16* og = g_o + (size_t)(r0 + 16 * warp) * DM + hg * 80;
#pragma unroll
    for (int i = 0; i < 5; i++) {
        const int id = lane + 32 * i, rr = id / 10, c = id - rr * 10;
        stg128(og + rr * DM + c * 8, lds128(ob + rr * Q_OROW + c * 16));
    }
    named_bar(2, 256);
    if (tid == 0) {
        mbar_arrive(s2u(&s_odone));
        asm volatile("fence.acq_rel.gpu;" ::: "memory");
        asm volatile("st.relaxed.gpu.global.u32 [%0], %1;" ::"l"(&g_oflag[layer][par * 8 + R][hg]), "r"(tag) : "memory");
    }
    if (tid == 0) TSTAMP(slot, 6);
    if (tid == 0) TSTAMP(slot, 7);
    } else if (tid == 0) {
        mbar_arrive_cta(s2u(&s_free), 0); mbar_arrive_cta(s2u(&s_free), 1);
    }
    {
        if (tid == 0) { TSTAMP(slot + 1, 0); TSTAMP(slot + 1, 1); }
        float acw[40];
        mbar_wait(s2u(&s_wfull), 0);
#pragma unroll 1
        for (int it = 0; it < 10; it++) {
            const int s = it & (O_ST - 1);
            mbar_wait(s2u(&s_ofull[s]), (it >> 2) & 1);
            if (it == 0 && tid == 0) TSTAMP(slot + 1, 3);
            const uint64_t da = mkdesc(sb + O_AOFF + it * O_AB, 0, 1024, 1), db = mkdesc(sb + O_BOFF + s * O_BB + wg * 10240, 16, 1024, 1);
            wg_fence();
#pragma unroll
            for (int ks = 0; ks < 4; ks++) wgmma_n80<1, 0>(acw, da + ks * 128, db + ks * 2, (ks > 0) ? 1 : (it > 0));
            wg_commit();
            wg_wait<1>();
            if (it > 0 && it <= 10 - O_ST && (tid & 127) == 0) {
                mbar_arrive_cta(s2u(&s_oempty[(it - 1) & (O_ST - 1)]), 0);
                mbar_arrive_cta(s2u(&s_oempty[(it - 1) & (O_ST - 1)]), 1);
            }
        }
        uint32_t res[20];
        mbar_wait(s2u(&s_res), 0);
        if (layer == 0) {
#pragma unroll
            for (int j = 0; j < 10; j += 2) {
                const int tok = 80 * wg + 8 * (j + (mi >> 1)) + mj, chunk = 2 * (warp & 3) + (mi & 1);
                ldsm_x4_t(res[2 * j], res[2 * j + 1], res[2 * j + 2], res[2 * j + 3], sb + O_ROFF + tok * 128 + ((chunk ^ (tok & 7)) << 4));
            }
        } else {
#pragma unroll
            for (int j = 0; j < 10; j++) {
                const int tok = 80 * wg + 8 * j, row = 16 * (warp & 3) + g;
                const uint32_t a = sb + O_ROFF + (tok >> 6) * 8192 + row * 128 + ((((tok >> 3) & 7) ^ g) << 4) + q * 4;
                res[2 * j] = lds32(a);
                res[2 * j + 1] = lds32(a + 8 * 128);
            }
        }
        wg_wait<0>();
        if (tid == 0) TSTAMP(slot + 1, 4);
        cluster_arrive_relaxed();
        const uint32_t tb = sb + O_BOFF + wg * 10240;
        auto trow = [&](int r) { return tb + (r >> 5) * O_BB + (r & 31) * O_TROW; };
        {
            const uint32_t ta = trow(16 * (warp & 3) + g) + q * 4;
#pragma unroll
            for (int j = 0; j < 10; j++) {
                sts32(ta + j * 16, pack2(bf_lo(res[2 * j]) + acw[4 * j], bf_hi(res[2 * j]) + acw[4 * j + 1]));
                sts32(ta + 8 * O_TROW + j * 16, pack2(bf_lo(res[2 * j + 1]) + acw[4 * j + 2], bf_hi(res[2 * j + 1]) + acw[4 * j + 3]));
            }
        }
        named_bar(5 + wg, 128);
        if (tid == 0) TSTAMP(slot + 1, 5);
        const int wt = tid & 127, t0 = w_r0 + 80 * wg;
#pragma unroll
        for (int i = 0; i < 5; i++) {
            const int id = wt + 128 * i, rr = id / 10, c = id - rr * 10;
            if (t0 + c * 8 < SEQ) stg128(outT + (size_t)(w_c0 + rr) * XP + t0 + c * 8, lds128(trow(rr) + c * 16));
        }
        if (wt < 120) {
            const int part = wt / 40, tp = wt - part * 40;
            float a0 = 0.f, a1 = 0.f, b0 = 0.f, b1 = 0.f;
#pragma unroll
            for (int i = 0; i < 22; i++) {
                if (i < 21 || part == 2) {
                    const uint32_t v = lds32(trow(part * 21 + i) + tp * 4);
                    const float lo = bf_lo(v), hi = bf_hi(v);
                    a0 += lo; b0 = fmaf(lo, lo, b0); a1 += hi; b1 = fmaf(hi, hi, b1);
                }
            }
            sts128(tb + 2 * O_BB + (part * 40 + tp) * 16, make_uint4(__float_as_uint(a0), __float_as_uint(b0), __float_as_uint(a1), __float_as_uint(b1)));
        }
        named_bar(5 + wg, 128);
        if (wt < 40 && t0 + 2 * wt < SEQ) {
            const uint4 p0 = lds128(tb + 2 * O_BB + wt * 16), p1 = lds128(tb + 2 * O_BB + (40 + wt) * 16), p2 = lds128(tb + 2 * O_BB + (80 + wt) * 16);
            auto F = [](uint32_t x) { return __uint_as_float(x); };
            asm volatile("red.global.add.v4.f32 [%0], {%1, %2, %3, %4};" ::"l"(sums + t0 + 2 * wt), "f"(F(p0.x) + F(p1.x) + F(p2.x)), "f"(F(p0.y) + F(p1.y) + F(p2.y)),
                         "f"(F(p0.z) + F(p1.z) + F(p2.z)), "f"(F(p0.w) + F(p1.w) + F(p2.w)) : "memory");
        }
        if (tid == 0) TSTAMP(slot + 1, 6);
    }
    cluster_wait();
    if (tid == 0) TSTAMP(slot + 1, 7);
    }
}
__device__ __forceinline__ void wgmma_h64_rs(uint32_t (&d)[16], const uint4& a, uint64_t db, int scale_d) {
    asm volatile("{\n.reg .pred p;\nsetp.ne.b32 p, %21, 0;\n"
                 "wgmma.mma_async.sync.aligned.m64n64k16.f16.f16.f16 {%0,%1,%2,%3,%4,%5,%6,%7,%8,%9,%10,%11,%12,%13,%14,%15}, {%16,%17,%18,%19}, %20, p, 1, 1, 1;\n}\n"
                 : "+r"(d[0]), "+r"(d[1]), "+r"(d[2]), "+r"(d[3]), "+r"(d[4]), "+r"(d[5]), "+r"(d[6]), "+r"(d[7]), "+r"(d[8]), "+r"(d[9]),
                   "+r"(d[10]), "+r"(d[11]), "+r"(d[12]), "+r"(d[13]), "+r"(d[14]), "+r"(d[15])
                 : "r"(a.x), "r"(a.y), "r"(a.z), "r"(a.w), "l"(db), "r"(scale_d));
}
__device__ __forceinline__ void wgmma_h32_rs(uint32_t (&d)[8], const uint32_t (&a)[4], uint64_t db, int scale_d) {
    asm volatile("{\n.reg .pred p;\nsetp.ne.b32 p, %13, 0;\n"
                 "wgmma.mma_async.sync.aligned.m64n32k16.f16.f16.f16 {%0,%1,%2,%3,%4,%5,%6,%7}, {%8,%9,%10,%11}, %12, p, 1, 1, 0;\n}\n"
                 : "+r"(d[0]), "+r"(d[1]), "+r"(d[2]), "+r"(d[3]), "+r"(d[4]), "+r"(d[5]), "+r"(d[6]), "+r"(d[7])
                 : "r"(a[0]), "r"(a[1]), "r"(a[2]), "r"(a[3]), "l"(db), "r"(scale_d));
}
__device__ __forceinline__ void wgmma_sp64_rs(float (&d)[32], const uint4& a, uint64_t db, uint32_t meta, int scale_d) {
    asm volatile("{\n.reg .pred p;\nsetp.ne.b32 p, %38, 0;\n"
                 "wgmma.mma_async.sp.sync.aligned.m64n64k32.f32.f16.f16 "
                 "{%0,%1,%2,%3,%4,%5,%6,%7,%8,%9,%10,%11,%12,%13,%14,%15,%16,%17,%18,%19,%20,%21,%22,%23,%24,%25,%26,%27,%28,%29,%30,%31}, "
                 "{%32,%33,%34,%35}, %36, %37, 0, p, 1, 1, 1;\n}\n"
                 : "+f"(d[0]), "+f"(d[1]), "+f"(d[2]), "+f"(d[3]), "+f"(d[4]), "+f"(d[5]), "+f"(d[6]), "+f"(d[7]), "+f"(d[8]), "+f"(d[9]),
                   "+f"(d[10]), "+f"(d[11]), "+f"(d[12]), "+f"(d[13]), "+f"(d[14]), "+f"(d[15]), "+f"(d[16]), "+f"(d[17]), "+f"(d[18]), "+f"(d[19]),
                   "+f"(d[20]), "+f"(d[21]), "+f"(d[22]), "+f"(d[23]), "+f"(d[24]), "+f"(d[25]), "+f"(d[26]), "+f"(d[27]), "+f"(d[28]), "+f"(d[29]),
                   "+f"(d[30]), "+f"(d[31])
                 : "r"(a.x), "r"(a.y), "r"(a.z), "r"(a.w), "l"(db), "r"(meta), "r"(scale_d));
}
__device__ __forceinline__ uint32_t hmul(uint32_t a, uint32_t b) { uint32_t d; asm("mul.rn.f16x2 %0, %1, %2;" : "=r"(d) : "r"(a), "r"(b)); return d; }
__device__ __forceinline__ uint32_t hfma(uint32_t a, uint32_t b, uint32_t c) { uint32_t d; asm("fma.rn.f16x2 %0, %1, %2, %3;" : "=r"(d) : "r"(a), "r"(b), "r"(c)); return d; }
__device__ __forceinline__ uint32_t hfms(uint32_t a, uint32_t b, uint32_t c) {
    uint32_t d;
    asm("{\n.reg .b32 n;\nneg.f16x2 n, %1;\nfma.rn.f16x2 %0, n, %2, %3;\n}" : "=r"(d) : "r"(a), "r"(b), "r"(c));
    return d;
}
__device__ __forceinline__ uint32_t hadd(uint32_t a, uint32_t b) { uint32_t d; asm("add.rn.f16x2 %0, %1, %2;" : "=r"(d) : "r"(a), "r"(b)); return d; }
__device__ __forceinline__ uint32_t hsub(uint32_t a, uint32_t b) { uint32_t d; asm("sub.rn.f16x2 %0, %1, %2;" : "=r"(d) : "r"(a), "r"(b)); return d; }
__device__ __forceinline__ uint4 ldg_tab(int tab, int t) { return __ldg((const uint4*)c_fft + tab * 128 + t); }
__device__ __forceinline__ uint32_t u4(const uint4& v, int i) { return i == 0 ? v.x : i == 1 ? v.y : i == 2 ? v.z : v.w; }

constexpr int F_S23 = 0;
constexpr int F_WG = 8192, F_WGB = 24576 + 6144;
constexpr int F_SMEM = F_WG + 3 * F_WGB + 1024;

__device__ __forceinline__ void fft_stage(const uint32_t (&u)[2][2][4], uint32_t eo, int warp4, int lane) {
    const int mi = lane >> 3, mj = lane & 7;
#pragma unroll
    for (int c = 0; c < 2; c++) {
        const uint32_t a = eo + (8 * warp4 + mj) * 128 + (((4 * c + mi) ^ mj) << 4);
        stsm_x4(a, hadd(u[c][0][0], u[c][1][0]), hadd(u[c][0][1], u[c][1][1]), hadd(u[c][0][2], u[c][1][2]), hadd(u[c][0][3], u[c][1][3]));
        stsm_x4(a + 4096, hsub(u[c][0][0], u[c][1][0]), hsub(u[c][0][1], u[c][1][1]), hsub(u[c][0][2], u[c][1][2]), hsub(u[c][0][3], u[c][1][3]));
    }
    fence_async_smem();
}
__device__ __forceinline__ void fft_forward(const uint4 (&a1)[4], const uint4 (&tw)[4], uint32_t eo, uint32_t s2, int bar, uint32_t (&X)[2][2][8]) {
    named_bar(bar, 128);
    uint32_t dr[16], di[16];
    const uint64_t de = mkdesc(eo, 4096, 1024, 1), d2 = mkdesc(s2, 16, 1024, 1);
    wg_fence();
    wgmma_h64_rs(dr, a1[0], de, 0);
    wgmma_h64_rs(di, a1[2], de + 256, 0);
    wgmma_h64_rs(dr, a1[1], de + 128, 1);
    wgmma_h64_rs(di, a1[3], de + 384, 1);
    wg_commit();
    wg_wait<0>();
#pragma unroll
    for (int c = 0; c < 2; c++) {
        uint32_t zr[2][4], zi[2][4];
#pragma unroll
        for (int p = 0; p < 2; p++)
#pragma unroll
            for (int i = 0; i < 4; i++) {
                const uint32_t r = dr[8 * c + 4 * p + i], m = di[8 * c + 4 * p + i], tr = u4(tw[p], i), ti = u4(tw[2 + p], i);
                zr[p][i] = hfms(m, ti, hmul(r, tr));
                zi[p][i] = hfma(m, tr, hmul(r, ti));
            }
        wg_fence();
        wgmma_h32_rs(X[c][0], zr[0], d2, 0);
        wgmma_h32_rs(X[c][1], zr[1], d2 + 4, 0);
        wgmma_h32_rs(X[c][0], zi[0], d2 + 2, 1);
        wgmma_h32_rs(X[c][1], zi[1], d2 + 6, 1);
        wg_commit();
    }
}

__global__ void __launch_bounds__(384, 1) conv_kernel(const bf16* __restrict__ xT, const float2* __restrict__ sums, bf16* __restrict__ out, int slot) {
    extern __shared__ __align__(1024) char smraw[];
    __shared__ __align__(8) uint64_t kbar;
    const uint32_t sb = (s2u(smraw) + 1023) & ~1023u;
    const int tid = threadIdx.x, warp = __shfl_sync(~0u, tid >> 5, 0), lane = tid & 31;
    const int wg = warp >> 2, w = warp & 3, t = tid & 127, g = lane >> 2, q = lane & 3, mi = lane >> 3, mj = lane & 7;
    const int npair = min(3, DM / 2 - 3 * (int)blockIdx.x), ch0 = 6 * blockIdx.x + 2 * wg;
    const uint32_t wb = sb + F_WG + wg * F_WGB, kc = wb + 24576;
    if (tid == 0) TSTAMP(slot, 0);
    if (tid == 0) {
        mbar_init(s2u(&kbar), 1);
        fence_mbar_init();
        mbar_expect(s2u(&kbar), 8192 + npair * 2 * KC_PITCH * 4);
#pragma unroll 1
        for (int i = 0; i < npair; i++) bulk_g2s(sb + F_WG + i * F_WGB + 24576, g_kc + (6 * blockIdx.x + 2 * i) * KC_PITCH, 2 * KC_PITCH * 4, s2u(&kbar));
        bulk_g2s(sb + F_S23, c_fft + 18 * 512, 8192, s2u(&kbar));
    }
    uint4 a1[4], tw[4];
#pragma unroll
    for (int i = 0; i < 4; i++) { a1[i] = ldg_tab(i, t); tw[i] = ldg_tab(8 + i, t); }
    const uint4 ko[2] = {ldg_tab(16, t), ldg_tab(17, t)};
    __syncthreads();
    pdl_launch();
    if (wg >= npair) return;
    uint32_t u[2][2][4], KH[2][2][8], oscale[2];
    mbar_wait(s2u(&kbar), 0);
#pragma unroll
    for (int c = 0; c < 2; c++) {
        const uint32_t e = min(max(lds32(kc + c * KC_PITCH * 4 + KC_MAX * 4) >> 23, 4u), 250u);
        const float sc = __uint_as_float((253u - e) << 23);
        oscale[c] = (e + 3u) * 0x00800080u;
#pragma unroll
        for (int h = 0; h < 2; h++)
#pragma unroll
            for (int j = 0; j < 4; j++) {
                const uint32_t o = u4(ko[h], j), b = kc + c * KC_PITCH * 4;
                u[c][h][j] = pack2h(__uint_as_float(lds32(b + (o & 0xFFFF))) * sc, __uint_as_float(lds32(b + (o >> 16))) * sc);
            }
    }
    fft_stage(u, wb + 8192, w, lane);
    if (tid == 0) TSTAMP(slot, 2);
    pdl_wait();
    if (tid == 0) TSTAMP(slot, 1);
    uint2 x[2][2][2];
    const int ra[2] = {16 * (8 * w + g) + 4 * q, 16 * (63 - 8 * w - g) + 4 * q};
    {
        uint4 s[2][2][2];
#pragma unroll
        for (int h = 0; h < 2; h++)
#pragma unroll
            for (int p = 0; p < 2; p++) {
                s[h][p][0] = ldg128(sums + 1024 * p + ra[h]);
                s[h][p][1] = ldg128(sums + 1024 * p + ra[h] + 2);
#pragma unroll
                for (int c = 0; c < 2; c++) x[c][h][p] = ldg64(xT + (size_t)(ch0 + c) * XP + 1024 * p + ra[h]);
            }
        fft_forward(a1, tw, wb + 8192, sb + F_S23, 1 + wg, KH);
#pragma unroll
        for (int i = 0; i < 4; i++) tw[i] = ldg_tab(4 + i, t);
        if (tid == 0) TSTAMP(slot, 5);
#pragma unroll
        for (int h = 0; h < 2; h++)
#pragma unroll
            for (int j = 0; j < 4; j++) {
                const uint4 sv = s[h][j >> 1][j & 1];
                const float4 v = make_float4(__uint_as_float(sv.x), __uint_as_float(sv.y), __uint_as_float(sv.z), __uint_as_float(sv.w));
                const float m0 = v.x * (1.0f / DM), m1 = v.z * (1.0f / DM);
                const float r0 = frsq(fmaxf(fmaf(v.y, 1.0f / DM, fmaf(-m0, m0, 1e-5f)), 1e-5f));
                const float r1 = frsq(fmaxf(fmaf(v.w, 1.0f / DM, fmaf(-m1, m1, 1e-5f)), 1e-5f));
                const float c0 = -m0 * r0, c1 = -m1 * r1;
#pragma unroll
                for (int c = 0; c < 2; c++) {
                    const uint32_t xv = (j & 1) ? x[c][h][j >> 1].y : x[c][h][j >> 1].x;
                    u[c][h][j] = pack2h(fmaf(bf_lo(xv), r0, c0), fmaf(bf_hi(xv), r1, c1));
                }
            }
    }
    if (tid == 0) TSTAMP(slot, 3);
    uint32_t X[2][2][8], Y[2][2][8];
    fft_stage(u, wb, w, lane);
    wg_wait<0>();
    fft_forward(a1, tw, wb, sb + F_S23, 1 + wg, X);
#pragma unroll
    for (int i = 0; i < 4; i++) a1[i] = ldg_tab(12 + i, t);
    const uint64_t d3 = mkdesc(sb + F_S23 + 4096, 16, 1024, 1);
#pragma unroll
    for (int c = 0; c < 2; c++) {
        wg_wait<1>();
        uint32_t pr[2][4], pi[2][4];
#pragma unroll
        for (int i = 0; i < 4; i++) {
            const uint32_t er = X[c][0][i], ei = X[c][0][4 + i], orr = X[c][1][i], oi = X[c][1][4 + i];
            const uint32_t ar = KH[c][0][i], ai = KH[c][0][4 + i], br = KH[c][1][i], bi = KH[c][1][4 + i];
            pr[0][i] = hfms(bi, oi, hfma(br, orr, hfms(ai, ei, hmul(ar, er))));
            pi[0][i] = hfma(bi, orr, hfma(br, oi, hfma(ai, er, hmul(ar, ei))));
            pr[1][i] = hfms(ai, oi, hfma(ar, orr, hfms(bi, ei, hmul(br, er))));
            pi[1][i] = hfma(ai, orr, hfma(ar, oi, hfma(bi, er, hmul(br, ei))));
        }
        wg_fence();
        wgmma_h32_rs(Y[c][0], pr[0], d3, 0);
        wgmma_h32_rs(Y[c][1], pr[1], d3 + 4, 0);
        wgmma_h32_rs(Y[c][0], pi[0], d3 + 2, 1);
        wgmma_h32_rs(Y[c][1], pi[1], d3 + 6, 1);
        wg_commit();
    }
    const uint32_t zb = wb + 8192;
#pragma unroll
    for (int c = 0; c < 2; c++) {
        if (c == 0) wg_wait<1>(); else wg_wait<0>();
        uint32_t zr[2][4], zi[2][4];
#pragma unroll
        for (int p = 0; p < 2; p++)
#pragma unroll
            for (int i = 0; i < 4; i++) {
                const uint32_t r = Y[c][p][i], m = Y[c][p][4 + i], tr = u4(tw[p], i), ti = u4(tw[2 + p], i);
                zr[i & 1][2 * p + (i >> 1)] = hfma(m, ti, hmul(r, tr));
                zi[i & 1][2 * p + (i >> 1)] = hfms(r, ti, hmul(m, tr));
            }
        const int kr = 4 * (mj >> 1) + (mj & 1) + 2 * (mj >> 2), ki = kr ^ 2;
#pragma unroll
        for (int h = 0; h < 2; h++) {
            const uint32_t a = zb + (2 * w + h) * 2048;
            stsm_x4(a + kr * 128 + (((4 * c + mi) ^ (kr & 7)) << 4), zr[h][0], zr[h][1], zr[h][2], zr[h][3]);
            stsm_x4(a + ki * 128 + (((4 * c + mi) ^ (ki & 7)) << 4), zi[h][0], zi[h][1], zi[h][2], zi[h][3]);
        }
    }
    fence_async_smem();
    named_bar(1 + wg, 128);
    float acc[32];
    const uint64_t dz = mkdesc(zb, 4096, 1024, 1);
    wg_fence();
#pragma unroll
    for (int ks = 0; ks < 4; ks++) wgmma_sp64_rs(acc, a1[ks], dz + ks * 256, 0x44EEEE44u, ks > 0);
    wg_commit();
    wg_wait<0>();
    if (tid == 0) TSTAMP(slot, 4);
#pragma unroll
    for (int c = 0; c < 2; c++)
#pragma unroll
        for (int p = 0; p < 2; p++) {
            uint32_t r[2][2];
#pragma unroll
            for (int j = 0; j < 2; j++) {
                const float* d = acc + 4 * (4 * c + 2 * p + j);
                const uint32_t y0 = pack2(d[0] + d[2], d[1] + d[3]), y1 = pack2(d[0] - d[2], d[1] - d[3]);
                asm("fma.rn.bf16x2 %0, %1, %2, %3;" : "=r"(r[0][j]) : "r"(y0), "r"(oscale[c]), "r"(j ? x[c][0][p].y : x[c][0][p].x));
                asm("fma.rn.bf16x2 %0, %1, %2, %3;" : "=r"(r[1][j]) : "r"(y1), "r"(oscale[c]), "r"(j ? x[c][1][p].y : x[c][1][p].x));
            }
#pragma unroll
            for (int h = 0; h < 2; h++) *(uint2*)(out + (size_t)(ch0 + c) * XP + 1024 * p + ra[h]) = make_uint2(r[h][0], r[h][1]);
        }
    if (tid == 0) TSTAMP(slot, 7);
}

constexpr int OT_SMEM = 120 * 1024;
__global__ void __launch_bounds__(256, 1) out_kernel(const bf16* __restrict__ xT, bf16* __restrict__ out, int slot) {
    constexpr int PITCH = 160 + 8;
    extern __shared__ __align__(1024) char smraw[];
    uint16_t* tile = (uint16_t*)smraw;
    const int tid = threadIdx.x, t0 = (blockIdx.x >> 2) * 64, c0 = (blockIdx.x & 3) * 160;
    if (tid == 0) TSTAMP(slot, 0);
    pdl_wait();
    if (tid == 0) TSTAMP(slot, 1);
    uint4 v[5];
#pragma unroll
    for (int i = 0; i < 5; i++) {
        const int id = tid + 256 * i, c = id >> 3, p = (id >> 2) & 1, k = id & 3;
        v[i] = ldg128(xT + (size_t)(c0 + c) * XP + p * 1024 + (t0 >> 1) + 8 * k);
    }
#pragma unroll
    for (int i = 0; i < 5; i++) {
        const int id = tid + 256 * i, c = id >> 3, p = (id >> 2) & 1, k = id & 3;
        uint16_t* t = tile + (16 * k + p) * PITCH + c;
        const uint32_t w[4] = {v[i].x, v[i].y, v[i].z, v[i].w};
#pragma unroll
        for (int j = 0; j < 4; j++) { t[(4 * j) * PITCH] = (uint16_t)w[j]; t[(4 * j + 2) * PITCH] = (uint16_t)(w[j] >> 16); }
    }
    __syncthreads();
#pragma unroll
    for (int i = 0; i < 5; i++) {
        const int id = tid + 256 * i, r = id / 20, c = id - r * 20;
        stg128(out + (size_t)(t0 + r) * DM + c0 + c * 8, *(const uint4*)(tile + r * PITCH + c * 8));
    }
    if (blockIdx.x == 0 && tid == 0) g_epoch = g_epoch + 1;
    if (tid == 0) TSTAMP(slot, 7);
}
typedef CUresult (*EncodeTiledFn)(CUtensorMap*, CUtensorMapDataType, cuuint32_t, void*, const cuuint64_t*, const cuuint64_t*, const cuuint32_t*,
                                  const cuuint32_t*, CUtensorMapInterleave, CUtensorMapSwizzle, CUtensorMapL2promotion, CUtensorMapFloatOOBfill);

static void make_map(EncodeTiledFn enc, CUtensorMap* m, const void* base, int rank, const cuuint64_t* dims, const cuuint64_t* strides,
                     const cuuint32_t* box, CUtensorMapSwizzle sw) {
    cuuint32_t es[3] = {1, 1, 1};
    enc(m, CU_TENSOR_MAP_DATA_TYPE_BFLOAT16, rank, (void*)base, dims, strides, box, es, CU_TENSOR_MAP_INTERLEAVE_NONE, sw,
        sw == CU_TENSOR_MAP_SWIZZLE_128B ? CU_TENSOR_MAP_L2_PROMOTION_L2_128B : CU_TENSOR_MAP_L2_PROMOTION_NONE, CU_TENSOR_MAP_FLOAT_OOB_FILL_NONE);
}

template <typename... KArgs, typename... Args>
static void launch(void (*kern)(KArgs...), int grid, int block, int smem, int cluster, bool pdl, Args... args) {
    cudaLaunchConfig_t cfg = {};
    cfg.gridDim = dim3(grid); cfg.blockDim = dim3(block); cfg.dynamicSmemBytes = smem; cfg.stream = cudaStreamPerThread;
    cudaLaunchAttribute at[2];
    int n = 0;
    if (cluster > 1) { at[n].id = cudaLaunchAttributeClusterDimension; at[n].val.clusterDim.x = cluster; at[n].val.clusterDim.y = 1; at[n].val.clusterDim.z = 1; n++; }
    if (pdl) { at[n].id = cudaLaunchAttributeProgrammaticStreamSerialization; at[n].val.programmaticStreamSerializationAllowed = 1; n++; }
    cfg.attrs = at; cfg.numAttrs = n;
    cudaLaunchKernelEx(&cfg, kern, KArgs(args)...);
}

struct HostState {
    bool ready = false;
    const void* key[4] = {nullptr, nullptr, nullptr, nullptr};
    CUtensorMap mX[2], mRes[2], mW, mWr, mWo, mO;
    bf16 *x1T, *x2T, *o;
    float2* sums;
};

extern "C" void kernel_launch(void* const* d_in, const int* in_sizes, int n_in, void* d_out, int out_size) {
    const bf16* x = (const bf16*)d_in[0];
    const bf16* wqkv = (const bf16*)d_in[1];
    const bf16* wo = (const bf16*)d_in[2];
    const bf16* lar = (const bf16*)d_in[4];
    const bf16* aim = (const bf16*)d_in[5];
    const bf16* cre = (const bf16*)d_in[6];
    const bf16* cim = (const bf16*)d_in[7];
    const bf16* logdt = (const bf16*)d_in[8];
    const bf16* dskip = (const bf16*)d_in[9];
    static HostState hs;
    if (!hs.ready || hs.key[0] != wqkv || hs.key[1] != wo || hs.key[2] != x) {
        void* fn = nullptr;
        cudaDriverEntryPointQueryResult qr;
        cudaGetDriverEntryPoint("cuTensorMapEncodeTiled", &fn, cudaEnableDefault, &qr);
        EncodeTiledFn enc = (EncodeTiledFn)fn;
        cudaGetSymbolAddress((void**)&hs.x1T, g_x1T);
        cudaGetSymbolAddress((void**)&hs.x2T, g_x2T);
        cudaGetSymbolAddress((void**)&hs.o, g_o);
        cudaGetSymbolAddress((void**)&hs.sums, g_sums);
        {
            cuuint64_t d[3] = {DM, 2, SEQ / 2}, s[2] = {DM * 2, DM * 4};
            cuuint32_t b[3] = {64, 1, 128}, br[3] = {64, 1, 32};
            make_map(enc, &hs.mX[0], x, 3, d, s, b, CU_TENSOR_MAP_SWIZZLE_128B);
            make_map(enc, &hs.mRes[0], x, 3, d, s, br, CU_TENSOR_MAP_SWIZZLE_128B);
            cuuint64_t d2[2] = {SEQ, DM}, s2[1] = {XP * 2};
            cuuint32_t b2[2] = {64, 64};
            make_map(enc, &hs.mX[1], hs.x2T, 2, d2, s2, b2, CU_TENSOR_MAP_SWIZZLE_128B);
            hs.mRes[1] = hs.mX[1];
        }
        { cuuint64_t d[2] = {3 * DM, DM}, s[1] = {3 * DM * 2}; cuuint32_t b[2] = {64, 32};
          make_map(enc, &hs.mW, wqkv, 2, d, s, b, CU_TENSOR_MAP_SWIZZLE_128B); }
        { cuuint64_t d[3] = {DM, DM, 3}, s[2] = {3 * DM * 2, DM * 2}; cuuint32_t b[3] = {16, 32, 3};
          make_map(enc, &hs.mWr, wqkv, 3, d, s, b, CU_TENSOR_MAP_SWIZZLE_32B); }
        { cuuint64_t d[2] = {DM, DM}, s[1] = {DM * 2}; cuuint32_t b[2] = {64, 64};
          make_map(enc, &hs.mWo, wo, 2, d, s, b, CU_TENSOR_MAP_SWIZZLE_128B); }
        { cuuint64_t d[2] = {DM, SEQ}, s[1] = {DM * 2}; cuuint32_t b[2] = {64, 80};
          make_map(enc, &hs.mO, hs.o, 2, d, s, b, CU_TENSOR_MAP_SWIZZLE_128B); }
        cudaFuncSetAttribute(attn_kernel, cudaFuncAttributeMaxDynamicSharedMemorySize, Q_SMEM);
        cudaFuncSetAttribute(conv_kernel, cudaFuncAttributeMaxDynamicSharedMemorySize, F_SMEM);
        cudaFuncSetAttribute(out_kernel, cudaFuncAttributeMaxDynamicSharedMemorySize, OT_SMEM);
        hs.key[0] = wqkv; hs.key[1] = wo; hs.key[2] = x;
        hs.ready = true;
    }
    const SsmParams sp = {lar, aim, cre, cim, logdt, dskip};
    for (int l = 0; l < 2; l++) {
        const bf16* xin = l ? hs.x2T : x;
        launch(attn_kernel, 130, 384, Q_SMEM, 2, l > 0, hs.mX[l], hs.mW, hs.mWr, hs.mWo, hs.mO, hs.mRes[l], xin, wqkv, wo, hs.x1T,
               hs.sums + l * SEQ, sp, l, 1 + 3 * l);
        launch(conv_kernel, 107, 384, F_SMEM, 1, true, (const bf16*)hs.x1T, (const float2*)(hs.sums + l * SEQ), hs.x2T, 3 + 3 * l);
    }
    launch(out_kernel, 128, 256, OT_SMEM, 1, true, (const bf16*)hs.x2T, (bf16*)d_out, 7);
}
```

```cpp
#include <cuda_runtime.h>
#include <cuda.h>
#include <cuda_bf16.h>
#include <cuda_fp16.h>
#include <stdint.h>

typedef __nv_bfloat16 bf16;

constexpr int SEQ = 2048;
constexpr int DM  = 640;
constexpr int XP  = SEQ + 64;
constexpr int NMODE = 192;

__device__ __forceinline__ uint32_t s2u(const void* p) { return (uint32_t)__cvta_generic_to_shared(p); }
__device__ __forceinline__ void mbar_init(uint32_t b, int c) { asm volatile("mbarrier.init.shared::cta.b64 [%0], %1;" ::"r"(b), "r"(c)); }
__device__ __forceinline__ void mbar_expect(uint32_t b, uint32_t bytes) { asm volatile("mbarrier.arrive.expect_tx.shared::cta.b64 _, [%0], %1;" ::"r"(b), "r"(bytes) : "memory"); }
__device__ __forceinline__ void mbar_arrive(uint32_t b) { asm volatile("mbarrier.arrive.shared::cta.b64 _, [%0];" ::"r"(b) : "memory"); }
__device__ __forceinline__ void mbar_arrive_cta(uint32_t b, uint32_t cta) {
    asm volatile("{\n.reg .b32 ra;\nmapa.shared::cluster.u32 ra, %0, %1;\nmbarrier.arrive.shared::cluster.b64 _, [ra];\n}" ::"r"(b), "r"(cta) : "memory");
}
__device__ __forceinline__ void mbar_wait(uint32_t b, uint32_t ph) {
    asm volatile("{\n.reg .pred p;\nW: mbarrier.try_wait.parity.shared::cta.b64 p, [%0], %1;\n@p bra D;\nbra W;\nD:\n}" ::"r"(b), "r"(ph) : "memory");
}
__device__ __forceinline__ void fence_mbar_init() { asm volatile("fence.mbarrier_init.release.cluster;" ::: "memory"); }
__device__ __forceinline__ void cluster_sync() { asm volatile("barrier.cluster.arrive.aligned;\nbarrier.cluster.wait.aligned;" ::: "memory"); }
__device__ __forceinline__ void pdl_wait() { asm volatile("griddepcontrol.wait;" ::: "memory"); }
__device__ __forceinline__ void pdl_launch() { asm volatile("griddepcontrol.launch_dependents;" ::: "memory"); }
__device__ __forceinline__ void named_bar(int id, int n) { asm volatile("bar.sync %0, %1;" ::"r"(id), "r"(n) : "memory"); }
__device__ __forceinline__ void fence_async_smem() { asm volatile("fence.proxy.async.shared::cta;" ::: "memory"); }

__device__ __forceinline__ void tma2d(uint32_t dst, const CUtensorMap* m, int c0, int c1, uint32_t bar) {
    asm volatile("cp.async.bulk.tensor.2d.shared::cluster.global.mbarrier::complete_tx::bytes [%0], [%1, {%3, %4}], [%2];"
                 ::"r"(dst), "l"(m), "r"(bar), "r"(c0), "r"(c1) : "memory");
}
__device__ __forceinline__ void tma2d_mc(uint32_t dst, const CUtensorMap* m, int c0, int c1, uint32_t bar, uint16_t mask) {
    asm volatile("cp.async.bulk.tensor.2d.shared::cluster.global.mbarrier::complete_tx::bytes.multicast::cluster [%0], [%1, {%3, %4}], [%2], %5;"
                 ::"r"(dst), "l"(m), "r"(bar), "r"(c0), "r"(c1), "h"(mask) : "memory");
}
__device__ __forceinline__ void tma3d(uint32_t dst, const CUtensorMap* m, int c0, int c1, int c2, uint32_t bar) {
    asm volatile("cp.async.bulk.tensor.3d.shared::cluster.global.mbarrier::complete_tx::bytes [%0], [%1, {%3, %4, %5}], [%2];"
                 ::"r"(dst), "l"(m), "r"(bar), "r"(c0), "r"(c1), "r"(c2) : "memory");
}
__device__ __forceinline__ void tma3d_mc(uint32_t dst, const CUtensorMap* m, int c0, int c1, int c2, uint32_t bar, uint16_t mask) {
    asm volatile("cp.async.bulk.tensor.3d.shared::cluster.global.mbarrier::complete_tx::bytes.multicast::cluster [%0], [%1, {%3, %4, %5}], [%2], %6;"
                 ::"r"(dst), "l"(m), "r"(bar), "r"(c0), "r"(c1), "r"(c2), "h"(mask) : "memory");
}
__device__ __forceinline__ void bulk_g2s(uint32_t dst, const void* src, uint32_t bytes, uint32_t bar) {
    asm volatile("cp.async.bulk.shared::cluster.global.mbarrier::complete_tx::bytes [%0], [%1], %2, [%3];"
                 ::"r"(dst), "l"(src), "r"(bytes), "r"(bar) : "memory");
}
__device__ __forceinline__ void prefetch_tmap(const CUtensorMap* m) { asm volatile("prefetch.tensormap [%0];" ::"l"(m) : "memory"); }

__device__ __forceinline__ void wg_fence() { asm volatile("wgmma.fence.sync.aligned;" ::: "memory"); }
__device__ __forceinline__ void wg_commit() { asm volatile("wgmma.commit_group.sync.aligned;" ::: "memory"); }
template <int N> __device__ __forceinline__ void wg_wait() { asm volatile("wgmma.wait_group.sync.aligned %0;" ::"n"(N) : "memory"); }
__device__ __forceinline__ uint64_t mkdesc(uint32_t addr, uint32_t lbo, uint32_t sbo, uint32_t mode) {
    return (uint64_t)((addr & 0x3FFFF) >> 4) | ((uint64_t)(lbo >> 4) << 16) | ((uint64_t)(sbo >> 4) << 32) | ((uint64_t)mode << 62);
}

__device__ __forceinline__ void mma16816(float (&c)[4], uint32_t a0, uint32_t a1, uint32_t a2, uint32_t a3, uint32_t b0, uint32_t b1) {
    asm("mma.sync.aligned.m16n8k16.row.col.f32.bf16.bf16.f32 {%0,%1,%2,%3},{%4,%5,%6,%7},{%8,%9},{%0,%1,%2,%3};"
                 : "+f"(c[0]), "+f"(c[1]), "+f"(c[2]), "+f"(c[3]) : "r"(a0), "r"(a1), "r"(a2), "r"(a3), "r"(b0), "r"(b1));
}
__device__ __forceinline__ void mma1688(float (&c)[4], uint32_t a0, uint32_t a1, uint32_t b0) {
    asm("mma.sync.aligned.m16n8k8.row.col.f32.bf16.bf16.f32 {%0,%1,%2,%3},{%4,%5},{%6},{%0,%1,%2,%3};"
                 : "+f"(c[0]), "+f"(c[1]), "+f"(c[2]), "+f"(c[3]) : "r"(a0), "r"(a1), "r"(b0));
}
__device__ __forceinline__ void ldsm_x4(uint32_t& r0, uint32_t& r1, uint32_t& r2, uint32_t& r3, uint32_t a) {
    asm volatile("ldmatrix.sync.aligned.m8n8.x4.shared.b16 {%0,%1,%2,%3}, [%4];" : "=r"(r0), "=r"(r1), "=r"(r2), "=r"(r3) : "r"(a) : "memory");
}
__device__ __forceinline__ void ldsm_x4_t(uint32_t& r0, uint32_t& r1, uint32_t& r2, uint32_t& r3, uint32_t a) {
    asm volatile("ldmatrix.sync.aligned.m8n8.x4.trans.shared.b16 {%0,%1,%2,%3}, [%4];" : "=r"(r0), "=r"(r1), "=r"(r2), "=r"(r3) : "r"(a) : "memory");
}
__device__ __forceinline__ void ldsm_x2(uint32_t& r0, uint32_t& r1, uint32_t a) {
    asm volatile("ldmatrix.sync.aligned.m8n8.x2.shared.b16 {%0,%1}, [%2];" : "=r"(r0), "=r"(r1) : "r"(a) : "memory");
}
__device__ __forceinline__ void ldsm_x2_t(uint32_t& r0, uint32_t& r1, uint32_t a) {
    asm volatile("ldmatrix.sync.aligned.m8n8.x2.trans.shared.b16 {%0,%1}, [%2];" : "=r"(r0), "=r"(r1) : "r"(a) : "memory");
}
__device__ __forceinline__ void stsm_x4(uint32_t a, uint32_t r0, uint32_t r1, uint32_t r2, uint32_t r3) {
    asm volatile("stmatrix.sync.aligned.m8n8.x4.shared.b16 [%0], {%1,%2,%3,%4};" ::"r"(a), "r"(r0), "r"(r1), "r"(r2), "r"(r3) : "memory");
}
__device__ __forceinline__ void stsm_x4_t(uint32_t a, uint32_t r0, uint32_t r1, uint32_t r2, uint32_t r3) {
    asm volatile("stmatrix.sync.aligned.m8n8.x4.trans.shared.b16 [%0], {%1,%2,%3,%4};" ::"r"(a), "r"(r0), "r"(r1), "r"(r2), "r"(r3) : "memory");
}
__device__ __forceinline__ void stsm_x2(uint32_t a, uint32_t r0, uint32_t r1) {
    asm volatile("stmatrix.sync.aligned.m8n8.x2.shared.b16 [%0], {%1,%2};" ::"r"(a), "r"(r0), "r"(r1) : "memory");
}
__device__ __forceinline__ uint32_t movm_t(uint32_t a) {
    uint32_t d;
    asm volatile("movmatrix.sync.aligned.m8n8.trans.b16 %0, %1;" : "=r"(d) : "r"(a));
    return d;
}
__device__ __forceinline__ uint32_t lds32(uint32_t a) { uint32_t v; asm volatile("ld.shared.u32 %0, [%1];" : "=r"(v) : "r"(a) : "memory"); return v; }
__device__ __forceinline__ uint32_t ldsv32(uint32_t a) { uint32_t v; asm volatile("ld.volatile.shared.u32 %0, [%1];" : "=r"(v) : "r"(a) : "memory"); return v; }
__device__ __forceinline__ void sts32(uint32_t a, uint32_t v) { asm volatile("st.shared.u32 [%0], %1;" ::"r"(a), "r"(v) : "memory"); }
__device__ __forceinline__ uint4 lds128(uint32_t a) { uint4 v; asm volatile("ld.shared.v4.u32 {%0,%1,%2,%3}, [%4];" : "=r"(v.x), "=r"(v.y), "=r"(v.z), "=r"(v.w) : "r"(a) : "memory"); return v; }
__device__ __forceinline__ void sts128(uint32_t a, uint4 v) { asm volatile("st.shared.v4.u32 [%0], {%1,%2,%3,%4};" ::"r"(a), "r"(v.x), "r"(v.y), "r"(v.z), "r"(v.w) : "memory"); }

__device__ __forceinline__ void stg128(void* p, uint4 v) { asm volatile("st.global.v4.u32 [%0], {%1,%2,%3,%4};" ::"l"(p), "r"(v.x), "r"(v.y), "r"(v.z), "r"(v.w) : "memory"); }

__device__ __forceinline__ uint4 ldg128(const void* p) { uint4 v; asm volatile("ld.global.v4.u32 {%0,%1,%2,%3}, [%4];" : "=r"(v.x), "=r"(v.y), "=r"(v.z), "=r"(v.w) : "l"(p) : "memory"); return v; }
__device__ __forceinline__ uint2 ldg64(const void* p) { uint2 v; asm volatile("ld.global.v2.u32 {%0,%1}, [%2];" : "=r"(v.x), "=r"(v.y) : "l"(p) : "memory"); return v; }
__device__ __forceinline__ uint32_t ldg32(const void* p) { uint32_t v; asm volatile("ld.global.u32 %0, [%1];" : "=r"(v) : "l"(p) : "memory"); return v; }

__device__ __forceinline__ uint32_t pack2(float lo, float hi) {
    uint32_t r;
    asm("cvt.rn.bf16x2.f32 %0, %1, %2;" : "=r"(r) : "f"(hi), "f"(lo));
    return r;
}
__device__ __forceinline__ float bf_lo(uint32_t v) { return __uint_as_float(v << 16); }
__device__ __forceinline__ float bf_hi(uint32_t v) { return __uint_as_float(v & 0xFFFF0000u); }
__device__ __forceinline__ float rbf(float x) { return __uint_as_float(pack2(0.f, x) & 0xFFFF0000u); }
__device__ __forceinline__ float ex2(float x) { float r; asm("ex2.approx.ftz.f32 %0, %1;" : "=f"(r) : "f"(x)); return r; }

__device__ __forceinline__ float2 ln_finish(float sum, float sumsq) {
    const float m = sum * (1.0f / DM);
    const float v = fmaxf(fmaf(sumsq, 1.0f / DM, -m * m), 0.f);
    float s, r;
    asm("sqrt.approx.ftz.f32 %0, %1;" : "=f"(s) : "f"(rbf(rbf(v) + 1e-5f)));
    asm("rcp.approx.ftz.f32 %0, %1;" : "=f"(r) : "f"(rbf(s)));
    return make_float2(m, r);
}
__device__ __forceinline__ uint32_t ln_finish_packed(float sum, float sumsq) {
    const float m = sum * (1.0f / DM);
    const float v = fmaxf(fmaf(sumsq, 1.0f / DM, -m * m), 0.f);
    float s;
    asm("sqrt.approx.ftz.f32 %0, %1;" : "=f"(s) : "f"(rbf(rbf(v) + 1e-5f)));
    return pack2(s, m);
}
__device__ __forceinline__ float frsq(float x) { float r; asm("rsqrt.approx.ftz.f32 %0, %1;" : "=f"(r) : "f"(x)); return r; }
__device__ __forceinline__ float frcp(float x) { float r; asm("rcp.approx.ftz.f32 %0, %1;" : "=f"(r) : "f"(x)); return r; }
__device__ __forceinline__ bool elect_one() {
    uint32_t p;
    asm volatile("{\n.reg .pred p;\nelect.sync _|p, 0xffffffff;\nselp.u32 %0, 1, 0, p;\n}" : "=r"(p));
    return p != 0;
}
__device__ __forceinline__ void cluster_arrive_relaxed() { asm volatile("barrier.cluster.arrive.relaxed.aligned;" ::: "memory"); }
__device__ __forceinline__ void cluster_wait() { asm volatile("barrier.cluster.wait.aligned;" ::: "memory"); }
template<int TA, int TB>
__device__ __forceinline__ void wgmma_n192(float (&d)[96], uint64_t da, uint64_t db, int scale_d) {
  asm volatile("{\n.reg .pred p;\nsetp.ne.b32 p, %98, 0;\n"
    "wgmma.mma_async.sync.aligned.m64n192k16.f32.bf16.bf16 "
    "{%0, %1, %2, %3, %4, %5, %6, %7, %8, %9, %10, %11, %12, %13, %14, %15, %16, %17, %18, %19, %20, %21, %22, %23, %24, %25, %26, %27, %28, %29, %30, %31, %32, %33, %34, %35, %36, %37, %38, %39, %40, %41, %42, %43, %44, %45, %46, %47, %48, %49, %50, %51, %52, %53, %54, %55, %56, %57, %58, %59, %60, %61, %62, %63, %64, %65, %66, %67, %68, %69, %70, %71, %72, %73, %74, %75, %76, %77, %78, %79, %80, %81, %82, %83, %84, %85, %86, %87, %88, %89, %90, %91, %92, %93, %94, %95}, %96, %97, p, 1, 1, %99, %100;\n}\n"
    : "+f"(d[0]), "+f"(d[1]), "+f"(d[2]), "+f"(d[3]), "+f"(d[4]), "+f"(d[5]), "+f"(d[6]), "+f"(d[7]), "+f"(d[8]), "+f"(d[9]), "+f"(d[10]), "+f"(d[11]), "+f"(d[12]), "+f"(d[13]), "+f"(d[14]), "+f"(d[15]), "+f"(d[16]), "+f"(d[17]), "+f"(d[18]), "+f"(d[19]), "+f"(d[20]), "+f"(d[21]), "+f"(d[22]), "+f"(d[23]), "+f"(d[24]), "+f"(d[25]), "+f"(d[26]), "+f"(d[27]), "+f"(d[28]), "+f"(d[29]), "+f"(d[30]), "+f"(d[31]), "+f"(d[32]), "+f"(d[33]), "+f"(d[34]), "+f"(d[35]), "+f"(d[36]), "+f"(d[37]), "+f"(d[38]), "+f"(d[39]), "+f"(d[40]), "+f"(d[41]), "+f"(d[42]), "+f"(d[43]), "+f"(d[44]), "+f"(d[45]), "+f"(d[46]), "+f"(d[47]), "+f"(d[48]), "+f"(d[49]), "+f"(d[50]), "+f"(d[51]), "+f"(d[52]), "+f"(d[53]), "+f"(d[54]), "+f"(d[55]), "+f"(d[56]), "+f"(d[57]), "+f"(d[58]), "+f"(d[59]), "+f"(d[60]), "+f"(d[61]), "+f"(d[62]), "+f"(d[63]), "+f"(d[64]), "+f"(d[65]), "+f"(d[66]), "+f"(d[67]), "+f"(d[68]), "+f"(d[69]), "+f"(d[70]), "+f"(d[71]), "+f"(d[72]), "+f"(d[73]), "+f"(d[74]), "+f"(d[75]), "+f"(d[76]), "+f"(d[77]), "+f"(d[78]), "+f"(d[79]), "+f"(d[80]), "+f"(d[81]), "+f"(d[82]), "+f"(d[83]), "+f"(d[84]), "+f"(d[85]), "+f"(d[86]), "+f"(d[87]), "+f"(d[88]), "+f"(d[89]), "+f"(d[90]), "+f"(d[91]), "+f"(d[92]), "+f"(d[93]), "+f"(d[94]), "+f"(d[95])
    : "l"(da), "l"(db), "r"(scale_d), "n"(TA), "n"(TB));
}

template<int TA, int TB>
__device__ __forceinline__ void wgmma_n48(float (&d)[24], uint64_t da, uint64_t db, int scale_d) {
  asm volatile("{\n.reg .pred p;\nsetp.ne.b32 p, %26, 0;\n"
    "wgmma.mma_async.sync.aligned.m64n48k16.f32.bf16.bf16 "
    "{%0, %1, %2, %3, %4, %5, %6, %7, %8, %9, %10, %11, %12, %13, %14, %15, %16, %17, %18, %19, %20, %21, %22, %23}, %24, %25, p, 1, 1, %27, %28;\n}\n"
    : "+f"(d[0]), "+f"(d[1]), "+f"(d[2]), "+f"(d[3]), "+f"(d[4]), "+f"(d[5]), "+f"(d[6]), "+f"(d[7]), "+f"(d[8]), "+f"(d[9]), "+f"(d[10]), "+f"(d[11]), "+f"(d[12]), "+f"(d[13]), "+f"(d[14]), "+f"(d[15]), "+f"(d[16]), "+f"(d[17]), "+f"(d[18]), "+f"(d[19]), "+f"(d[20]), "+f"(d[21]), "+f"(d[22]), "+f"(d[23])
    : "l"(da), "l"(db), "r"(scale_d), "n"(TA), "n"(TB));
}

__device__ __forceinline__ void wgmma_rs64(float (&d)[32], const uint4& a, uint64_t db, int scale_d) {
  asm volatile("{\n.reg .pred p;\nsetp.ne.b32 p, %37, 0;\n"
    "wgmma.mma_async.sync.aligned.m64n64k16.f32.bf16.bf16 {%0,%1,%2,%3,%4,%5,%6,%7,%8,%9,%10,%11,%12,%13,%14,%15,%16,%17,%18,%19,%20,%21,%22,%23,%24,%25,%26,%27,%28,%29,%30,%31}, {%32,%33,%34,%35}, %36, p, 1, 1, 1;\n}\n"
    : "+f"(d[0]), "+f"(d[1]), "+f"(d[2]), "+f"(d[3]), "+f"(d[4]), "+f"(d[5]), "+f"(d[6]), "+f"(d[7]), "+f"(d[8]), "+f"(d[9]), "+f"(d[10]), "+f"(d[11]), "+f"(d[12]), "+f"(d[13]), "+f"(d[14]), "+f"(d[15]), "+f"(d[16]), "+f"(d[17]), "+f"(d[18]), "+f"(d[19]), "+f"(d[20]), "+f"(d[21]), "+f"(d[22]), "+f"(d[23]), "+f"(d[24]), "+f"(d[25]), "+f"(d[26]), "+f"(d[27]), "+f"(d[28]), "+f"(d[29]), "+f"(d[30]), "+f"(d[31])
    : "r"(a.x), "r"(a.y), "r"(a.z), "r"(a.w), "l"(db), "r"(scale_d));
}

__device__ __forceinline__ void wgmma_rs16(float (&d)[8], const uint4& a, uint64_t db, int scale_d) {
  asm volatile("{\n.reg .pred p;\nsetp.ne.b32 p, %13, 0;\n"
    "wgmma.mma_async.sync.aligned.m64n16k16.f32.bf16.bf16 {%0,%1,%2,%3,%4,%5,%6,%7}, {%8,%9,%10,%11}, %12, p, 1, 1, 1;\n}\n"
    : "+f"(d[0]), "+f"(d[1]), "+f"(d[2]), "+f"(d[3]), "+f"(d[4]), "+f"(d[5]), "+f"(d[6]), "+f"(d[7])
    : "r"(a.x), "r"(a.y), "r"(a.z), "r"(a.w), "l"(db), "r"(scale_d));
}

__device__ const __align__(1024) uint32_t c_fft[11264] = {
0x2ddc2dba,0x2fe62eb5,0x2ed02eb5,0xafffaf6e,0x2e1f2dfe,0x2e3f2fbc,0x2f022ee9,0xad27af30,0x2e5e2e3f,0x1fd92b5e,0x2f302f1a,0x244ea875,0x2e992e7c,0xad96a993,0x2f5a2f46,0x2e992c32,
0xad00ad72,0xa17eac32,0xa17ea515,0xabb79cb6,0xac07ac87,0x2dfe29f1,0x1fd99648,0xafedae99,0xa9f1ab05,0x2fd42fbc,0x26a1244e,0xad96af91,0xa765a8d5,0x2aaa2e3f,0x29932875,0x2515a8d5,
0xae99adfe,0xb000aee9,0xaf6eafbc,0x2c872f30,0xaf80af1a,0xac32af02,0xae7caf02,0xaaaa217e,0xaff4afc9,0x2b5e9cb6,0xad27addc,0xaff4ae7c,0xafedb000,0x2ffc2eb5,0xab05ac5d,0xacd8af5a,
0x2c072d27,0x9fd92bb7,0xadfead00,0x2fed2e1f,0x25db2993,0xaf6eacb0,0xaf6eaed0,0x2c5d2f46,0xa5151648,0xaddcafdd,0xafffafd4,0xac321648,0xabb7a934,0x28d5a814,0xafa0afed,0xaff4af30,
0x2f302e3f,0x2fed2f1a,0x28142b5e,0x2934a875,0x30002fc9,0x26a12ddc,0xa5db1cb6,0x30002e7c,0x2f462fd4,0xaed0aa4e,0xacb0aa4e,0x29932e99,0x2d272e5e,0xae3faffc,0xaf02adfe,0xae1fa814,
0xa9f1acd8,0x26a1ab05,0x2fd42ffc,0xad96afed,0x2515a30e,0x2fff2e1f,0x2ddc2f1a,0x2c32a30e,0x2d272aaa,0x28752e7c,0x28752c32,0x2fa02f80,0x2f912e99,0xaee9a9f1,0xa8141648,0x9fd92c87,
0xafa0ae7c,0xafafaf46,0x2d002993,0xafa0ac32,0xaf91b000,0x244eac5d,0x2fbc2eb5,0xab05af5a,0xac87ae5e,0x30002dfe,0x2f6e2ffc,0x2e992814,0x1cb6a875,0x25152e1f,0x2c322e1f,0x2d722ff4,
0x27652c87,0xa9932a4e,0xaaaaadba,0xa5152c87,0xabb7a44e,0xafa0af30,0x28d59fd9,0xaff4ae5e,0xaf91ae1f,0x2814abb7,0x2ee92d00,0x1fd9ad27,0xaf5aafff,0x2fd42ed0,0x2fd42fe6,0x30002ddc,
0x2f462f6e,0x2c322fdd,0x2e7c2fdd,0xa993b000,0xab5e2934,0xafafacd8,0xad00244e,0x2f1a2dfe,0xaee9afaf,0x2f30a17e,0xadfeaff8,0xafbca30e,0x2c5da765,0xa9f12ddc,0x2d969cb6,0x2c5dacb0,
0x2bb7a993,0x2f1aa515,0x2f1a2765,0xaff4aaaa,0x2e5e2fd4,0xab052dba,0x29342f6e,0x2ee9a6a1,0xadba1fd9,0xa5dbafed,0xafddac07,0xaa4e2dfe,0xacb0aff8,0x2ddc2f02,0x9cb6ae3f,0xa765aff8,
0xaeb5af91,0xaa4eafed,0x9648ae5e,0xac5d2d4d,0x2ddca17e,0x2e7c2e3f,0x2fc92e3f,0x1cb6afa0,0x2bb72fe6,0xaff8a993,0xab5e2aaa,0x2bb72fc9,0xafbcaa4e,0x2f30a5db,0xadfeafdd,0xaee9adba,
0xacd828d5,0xaf91230e,0xaf30af02,0x2c072fa0,0xac5dafff,0x2dbaac32,0x2dbaa515,0xae99addc,0x2fc929f1,0xa9932eb5,0x2aaa2fdd,0x2fe629f1,0xa30e2dfe,0xa17eafed,0xaff8ac07,0xafaf1fd9,
0x2dfe2faf,0x28142ff8,0xae5e217e,0x2ffc230e,0xaf5aa515,0xac87af46,0xa6a1af80,0xaf5a2765,0x1cb6ae99,0x2e7c2dba,0x2fc92dba,0x2ddcac5d,0x2f1a2ee9,0xafafab05,0xad002934,0xab5e2e5e,
0x2dbaa814,0x2fdd9fd9,0x25db2f91,0x2a4eaee9,0x27652faf,0xaf4628d5,0xaf80ae1f,0xa5152faf,0xafa0addc,0x2e3fac32,0x2e3fa515,0xa17eafff,0x2dfea6a1,0xacd82dba,0x244e2f6e,0x29342fd4,
0xad27afc9,0xa30eafff,0x2faf2d72,0xad27ae7c,0x2ffc2a4e,0x28142fdd,0xae5e25db,0x2dfe2dba,0xac5d2c07,0xaa4eaf91,0x9648af30,0xaeb5acd8,0xa993aff4,0x2c322f1a,0x2e7c2f1a,0x2f462bb7,
0xae7c26a1,0xafff1648,0x2d72aa4e,0xafc926a1,0x230eaee9,0x2ff89fd9,0x217e2f91,0x2fafa814,0x2d4d2fa0,0xafed230e,0xae5eaf02,0xaf9128d5,0xb000aaaa,0x2fdda515,0x2fdd2765,0x2f6ea993,
0x9cb63000,0xacb02fd4,0xa7652fd4,0x2ddcaf5a,0x217eaffc,0x2ff4ac07,0x2875afbc,0xaff82934,0xa44e2ff4,0xadfea8d5,0xa9342fa0,0x2cd82bb7,0x25dbafe6,0x16482f46,0x29f1af80,0x25dbafc9,
0x2ff41cb6,0x2e1f2765,0x2e1f2cb0,0xa875addc,0xafbca5db,0x1fd9af5a,0xad4dad96,0xacd82fdd,0x2f5a2934,0xaeb52ee9,0x2c5d2e5e,0x3000ab05,0xaed0ab5e,0x2f80a30e,0xaaaaaf02,0xacb0ab5e,
0x25dbaffc,0x2d96afbc,0x2f5aac07,0xafdd2934,0xaaaa2fa0,0xafc92875,0xafe62875,0x29932d27,0x2d00aed0,0x28d52d72,0x2ff89cb6,0x2d00afe6,0xae5e2d96,0x2d4dafd4,0xaf91a6a1,0xafed29f1,
0xafbca17e,0xad4da875,0x1fd9aff4,0xacd82ff8,0x2e992aaa,0xaa4e2fe6,0xaa4e2fc9,0x2fd4a993,0xacb0ad96,0x2fffac87,0x2d72aeb5,0xa765ad96,0x28752f30,0xab5eac07,0xaf1a2cd8,0xae3f2f91,
0xa9342ff4,0xae5e2fa0,0xaee9a8d5,0x2b052bb7,0x2d96aed0,0x2eb59cb6,0x2c872d72,0x2d96afe6,0xaf802c5d,0x2765af6e,0xa515af6e,0xaf4625db,0x2ff8a44e,0xaff42d4d,0xa8752ffc,0xa17e2ee9,
0x2f5a244e,0x2c5d2934,0xaeb52dfe,0x3000acd8,0xacb0ad00,0x2d72aff8,0x2fffa8d5,0xa765ad00,0x217e2f80,0xaf022515,0xaf02a765,0xaf1a2f46,0x2b05afdd,0xa8142f5a,0x2c072d96,0x2d4d25db,
0x2b5eafe6,0x2f02af80,0x230e2f46,0x2b5eafc9,0xaf302d96,0xacd8a6a1,0x2c07afd4,0xaf9129f1,0x2fdda44e,0xad962ffc,0xaf5a2d4d,0xa5db2ee9,0xad72abb7,0x2e7ca17e,0x2fc9a17e,0x2fffad00,
0xaed0a5db,0xaaaaa9f1,0x2f809648,0xacb0a5db,0x28752e5e,0xaf1a2f91,0xab5ead4d,0xae3f2fed,0x2b05aff8,0x2c072875,0xa8142ff4,0x2d4d217e,0xaf6e2d72,0x2eb5afc9,0x2eb5ae7c,0x2dbaafff,
0xaf802f5a,0xafc92e99,0xafe62e99,0x2f46ad96,0x28d52b05,0xaf022fed,0x230e2cd8,0x2fa0affc,0x2fbcaf02,0xa9342d27,0x2ffcae1f,0x2c07ae3f,0xa6a1ac32,0x2a4e9cb6,0x9648ad72,0xa6a1a515,
0x28752aaa,0xa8d52cb0,0xa8d52ed0,0x2e3faf80,0x2fedaeb5,0x29349648,0x2f30aa4e,0x2814ac5d,0x1648ad4d,0x2e99acd8,0x2c87afbc,0xa9f11fd9,0xafe62d27,0x2fffafaf,0xaddc230e,0xaed02d27,
0x2fd4af30,0x2f6eae5e,0x2dbaa44e,0xa6a19fd9,0x1cb6ad27,0x2fe6aff4,0x2ed0aff4,0xad722b5e,0xafaf2cb0,0x2e1faf46,0xa8d5a993,0xafaf2ed0,0xac072f6e,0x2934ac87,0xaffc2e99,0xafbc3000,
0xa44eab5e,0x2b05ad00,0x2f91afaf,0xafbc2f1a,0xafd42d72,0x1648a765,0x1648acb0,0xafdd2fff,0xac322f5a,0xaaaa26a1,0xaf802c87,0xae7c2f5a,0x2d009fd9,0xae1f2cd8,0xad272fbc,0xabb72d4d,
0xaffc2f02,0xaee92e1f,0x244ead27,0xad4d2e3f,0xa9f12e7c,0xafdd2f80,0xaeb52aaa,0xa9f12c32,0x2d72a5db,0xafe63000,0xaed03000,0x9cb626a1,0x2fa0afbc,0xaf022f91,0x230e2b05,0x28d5a44e,
0x96482c07,0xac872d4d,0xae992b05,0x29f1a814,0x2ed0abb7,0xa9932b5e,0xaf462ff8,0x2cb0abb7,0x2f1aafff,0xa30e2765,0xa30e2cb0,0x2e1fad72,0x1fd9ac5d,0x244e9648,0x2e5eaa4e,0x2f30aeb5,
0x2ff8aed0,0x2e3faddc,0xaf022fff,0x2ff8afe6,0x2d4daf6e,0x2ee9ae99,0xa44e2c87,0x2ffcb000,0xa6a1a814,0x2f6eaf30,0x2dbaa934,0x2fd4afed,0xaf462d00,0x2fc9afa0,0x2fe6afa0,0x2f80afaf,
0x2515ac5d,0x2d72ad96,0x1cb629f1,0x2c32ac5d,0xad002814,0x2d27ad4d,0x2e1fab05,0x2bb7ac07,0xaffc2f1a,0x2cd8ad00,0x2fedafaf,0x2b05ab5e,0xadba2f80,0x2c87acb0,0x2c87aed0,0x2a4eaaaa,
0x2f802f6e,0x2fc92fdd,0x2fe62fdd,0xaf46b000,0x2fa02f91,0x2bb72e5e,0x2ff42fed,0xa8d5ad4d,0x2fbc2faf,0xa934217e,0x2ffc2ff8,0x2c07230e,0x2fd42fc9,0xaf5aad72,0x30002fff,0x2fd42e7c,
0x2bb72aaa,0x2f1a2cb0,0x2f1a2ed0,0xaff4af80,0x2cd82c5d,0x2f303000,0x2f912f5a,0xac07aeb5,0x2dba2d4d,0x25db2cd8,0x2fdd2fbc,0x2a4e9fd9,0x2e7c2e1f,0xad72a875,0x2fff2ff4,0x2fc92e1f,
0xa6a1a934,0x29f1a44e,0x2d962cd8,0xafd4adfe,0x1cb6a17e,0x2fe62e3f,0x2ed02e3f,0xad72afa0,0x28752515,0x2d272f80,0x2fa02f46,0x2875a765,0x2c072a4e,0xa93425db,0x2ffc2fdd,0x2fbc2dba,
0xae5eaf1a,0xa934ae3f,0x2b052875,0xaee9ab5e,0xac5dad72,0x2dba2765,0x2dba2cb0,0xae99afff,0xa765aa4e,0x2f802fd4,0x2f462e99,0x2515aa4e,0x230e9fd9,0x217e2cd8,0x2ff82fbc,0x2faf2d4d,
0xaffcafaf,0xaee9aff8,0x244ea17e,0xad4da30e,0xaf6eafe6,0x25dbaaaa,0x2c5d2993,0xaf6eafc9,0xad72ae99,0x2fe62dba,0x2ed02dba,0x1cb6ac5d,0xa8d5ac07,0x2bb72f30,0x2ff42f91,0x2fa02cd8,
0xadbaac07,0xafddad4d,0xa5dbab05,0xaa4e2814,0xafc9af02,0xaaaaaf1a,0x2993217e,0xafe6af02,0xafa0afff,0x2e3f2765,0x2e3f2cb0,0xa17ead72,0xad4daeb5,0x2e5e3000,0x2fed2f5a,0x2f912c5d,
0xa17e2765,0xad001cb6,0xabb7addc,0xa17e2cb0,0xad4daa4e,0xaee9afdd,0x244ea5db,0xaffcadba,0xafd4aee9,0x29f1a934,0x2d962b05,0xa6a1ae5e,0xaf46aff4,0x2fc92f1a,0x2fe62f1a,0x2f802bb7,
0x2cb02eb5,0x1cb62dba,0xaddcaf6e,0x27652eb5,0xa30e2814,0xaff8ad4d,0xa17eab05,0xafafac07,0xadfeab5e,0xa44eae3f,0x2cd82875,0xa934af1a,0xb000af80,0x2fdd2cb0,0x2fdd2ed0,0x2f6e2aaa,
0x2d723000,0x25152fd4,0x2c322fd4,0x1cb6af5a,0xae1f9fd9,0xae3faee9,0xaf02a814,0x2d272f91,0xacd8aff4,0x2ffc28d5,0xab05afa0,0xafedabb7,0x2e992515,0xad962aaa,0x2f5a2993,0x2e99a765,
0x2ff42ddc,0x2e1f2ed0,0x2e1f2fe6,0xa875afff,0xa8142c87,0xaffca9f1,0xadfe1648,0x2e5e2e99,0xaf5aaf30,0x2eb5a814,0xac5dafed,0xb000a934,0x2c32a8d5,0xa9932e3f,0x2f462875,0x2e7ca8d5,
0x2e991fd9,0x30002814,0x2f6e2ee9,0xac87af91,0x29932fa0,0xaed02875,0xacb02875,0x2f462d27,0xaff4ac32,0x2b5eaddc,0xad27afff,0xaff4a515,0x244ead96,0x1fd92fd4,0x2f3026a1,0x2e5ea9f1,
0x2814ad27,0x2dfeabb7,0x2ffc2d00,0xae5eae1f,0x2e992f80,0xaa4e2e7c,0xaa4e2c32,0x2fd42aaa,0xae7c1648,0x9cb6afdd,0xaddcafd4,0xafc91648,0xa875af91,0x2b5e2fbc,0x2f1a244e,0x2e3fab05,
0xab05aff4,0x244eafa0,0x2fbc28d5,0xaf91abb7,0x30002c32,0x26a12fff,0xa5db2ddc,0x30002515,0xaaaa2c5d,0xac32af6e,0xae7caf6e,0xaf8025db,0xad27afed,0x2e3f2dfe,0x2f021fd9,0x2e1fac07,
0xaf5aae5e,0xac5daf30,0x2eb59fd9,0xb000a44e,0x2e7ca30e,0x2ddc2e1f,0x1cb62f1a,0x2fc9a30e,0x217e2f46,0xaf02acb0,0xaf02aed0,0xaf1a2993,0xaf30ae99,0x2fbc29f1,0x2ee99648,0x2dfeac87,
0xafa0a515,0xafafa993,0x2d00aaaa,0xafa02765,0x2934ad96,0x2fed26a1,0x28142fd4,0x2f30a9f1,0x2c872fed,0xb0009fd9,0xaf6eadfe,0xae992c07,0xafffabb7,0x2fe6a17e,0x2ed0a17e,0x2ddcad00,
0xac322c87,0xaf462a4e,0x2993adba,0xae7c2c87,0xa875afed,0x2f1aab05,0x2b5e2ffc,0x2e3facd8,0x2f302e1f,0xaee92bb7,0xafbcad00,0xadfe2d27,0xaf6e9cb6,0x2eb5ac32,0x2eb5a515,0x2dbaad72,
0xaaaa2f5a,0xaed02e99,0xacb02e99,0x2f80ad96,0x2b5eaf30,0x2fafa44e,0x2d00ae5e,0xaf1a9fd9,0xac072f02,0xab05ad27,0xad4d2e1f,0x28142e3f,0x2c5daed0,0xa9f12fff,0x2d96addc,0x2c5dafe6,
0x28752f80,0xa8d52fe6,0xa8d52fc9,0x2e3faf46,0xa44eafd4,0x2f91adba,0x2b05af6e,0xafbc26a1,0x96482ffc,0xae99a44e,0xac872ee9,0x29f12d4d,0x2515aff8,0x1cb62f02,0x2d72ae3f,0x2c32aff8,
0x2eb52b05,0x2a4e2cd8,0x16482fed,0x2c5daffc,0xad72ad27,0x2cb0aff4,0x2765aff4,0xafff2b5e,0x2bb72e7c,0xaff82aaa,0xab5e2f80,0x2bb72c32,0xa814af6e,0x2b052c87,0x2d4dae99,0x2c07b000,
0x2feda8d5,0x2f30a30e,0x29342f02,0x2814afa0,0xafd49cb6,0x1648aed0,0x1648afe6,0xafdd2d72,0x2ed029f1,0xaf462eb5,0xa9932fdd,0x2cb029f1,0xad00ad4d,0x2e1f244e,0x2d27aee9,0x2bb7affc,
0x2d4daf02,0x2fbcae1f,0x2cd82d27,0x9fd9ae3f,0xaf5a2cb0,0xac87a993,0xa6a1af46,0xaf5a2ed0,0x2fffa5db,0xacb03000,0xa7653000,0x2d7226a1,0xaf1aa814,0x2fafa934,0x2d00af30,0x2b5eafed,
0x1648afbc,0x2c87affc,0x2e992934,0xa9f1ac07,0xac322faf,0xaf8028d5,0xaaaaae1f,0xae7c2faf,0x2f1aad72,0xa30e2ed0,0xa30e2fe6,0x2e1f1cb6,0xaffc26a1,0x2fedadba,0x2cd8af6e,0x2b05afd4,
0xad27ac32,0xa30ead72,0x2faf9cb6,0xad27a515,0x1fd92f6e,0xafbc2e99,0xacd8ac87,0xad4d3000,0x2c5dafbc,0x2a4e2b05,0x16482f91,0x2eb5a44e,0xaf802d00,0x2ed0afa0,0x2cb0afa0,0x2aaaafaf,
0xafe626a1,0xaddc1648,0x2fffaa4e,0xaed026a1,0x2d002c07,0xad272ffc,0xae1fa934,0xabb72fbc,0x1fd9afa0,0x2e5ea30e,0x244e2f02,0x2f30a8d5,0xadba2f46,0x2c87afe6,0x2c87afc9,0x2a4eaf80,
0xafff2d96,0xae7c2c5d,0xafc92c5d,0x2d72a9f1,0xa17e2dfe,0xaff42fbc,0xa8752ee9,0x2ff8af30,0x2fedad00,0xad4d2f1a,0x2f91ab5e,0x2e5eafaf,0x25dbae7c,0x16482993,0x29f1af46,0x25dbac32,
0xae3f2fff,0xaff82fc9,0xaff82e7c,0x2f02ad72,0x2c0725db,0xadfe2f5a,0x9fd92d96,0x2fedafdd,0x2f6eaf91,0xa6a12c07,0x2fd4acd8,0x2dbaaf30,0xa765ab5e,0x2aaaa30e,0x2993af02,0x2515ab5e,
0xa5db2dfe,0xad962ee9,0xaf5a2fbc,0x2fddaf30,0x2f46ab5e,0xa7652bb7,0x25152bb7,0x2f80aff8,0x2d00afc9,0x28d59cb6,0x2ff8addc,0x2d00ae7c,0xacd89648,0x2dfeac5d,0x2934aeb5,0x244eaa4e,
0x2c07217e,0x9fd92875,0xadfe2ff4,0x2fedaff8,0x2fddaf46,0x29f1a515,0x29f12765,0x2eb5af80,0x2515ad96,0x2ddcac87,0x2fffaeb5,0x2c32ad96,0xaf022b05,0x2fa0aee9,0x28d5ae5e,0x230ea934,
0x2f91ad00,0x2cd8ab5e,0xac072f1a,0x2f30afaf,0x2d96afc9,0x2eb5addc,0x2c879cb6,0x2d96ae7c,0xa993a6a1,0x2fc9af5a,0x2fe6af5a,0x2aaaac87,0xaff82e5e,0x2ff4affc,0x2875adfe,0x217ea814,
0x2f6eafed,0x2fd4af91,0xa6a12d4d,0x2dbaae5e,0x2515ad00,0x2fffaff8,0x2ddca8d5,0x2c32ad00,0xae1f2993,0x2fafafe6,0x2fafafc9,0x28d5aaaa,0xaf912fdd,0x2ee9af5a,0x2814ad96,0x1fd9a5db,
0x2b5eae7c,0x2f02af46,0x230e2993,0x2b5eac32,0xab059648,0x2e5eaeb5,0x2ee9ac5d,0x2934aa4e,0xafdd2e5e,0x2d96adfe,0x2f5aaffc,0x25dba814,0xaddc2faf,0x2cb0ad27,0x2765ad27,0x1cb6a30e,
0xa765a5db,0x2993a9f1,0x2aaa9648,0x2515a5db,0xaf022cd8,0x28d5a934,0x2fa0adfe,0x230ea44e,0xaf912ff8,0x2814a875,0x2ee9aff4,0x1fd9a17e,0xaa4e2ddc,0x26a1a765,0x26a1acb0,0x16489cb6,
0x2d722d96,0x25152c5d,0x2c322c5d,0x1cb6a9f1,0x2d272d4d,0xad00a814,0x2bb72c07,0x2e1f2b05,0x2cd82d00,0xaffcaf1a,0x2b052b5e,0x2fed2faf,0x2c872cb0,0xadbaaf80,0x2a4e2aaa,0x2c872ed0,
0x2e3f2ddc,0x2ff82ed0,0x2ff82fe6,0xaf02afff,0x2ee92e99,0x2d4d2f6e,0x2ffc3000,0xa44eac87,0x2f6e2f30,0xa6a12814,0x2fd42fed,0x2dba2934,0x2fc92fa0,0xaf46ad00,0x2f802faf,0x2fe62fa0,
0xac87ad4d,0x9648ac07,0x29f12814,0xae99ab05,0xa993ab5e,0x2ed02bb7,0x2cb02bb7,0xaf46aff8,0xa30ea765,0x2f1a2fff,0x2e1f2d72,0xa30eacb0,0x244e1648,0x1fd92c5d,0x2f302eb5,0x2e5e2a4e,
0xaee9ae1f,0xaffcaf02,0xad4dae3f,0x244e2d27,0xafddaf80,0xa9f1ae7c,0xa9f1ac32,0xaeb5aaaa,0xafe6b000,0x2d7225db,0x9cb6a6a1,0xaed0b000,0xaf02af91,0x2fa02fbc,0x28d5244e,0x230eab05,
0x2b052d00,0xa44e2b5e,0xafbcaf1a,0x2f912faf,0x16482765,0xafd4ad72,0xafddafff,0x16482cb0,0xaaaaa6a1,0xac32af5a,0xae7caf5a,0xaf80ac87,0xae1facd8,0x2d001fd9,0xabb7ad4d,0xad27afbc,
0x2f6e2e5e,0x2fd42f30,0xa6a11fd9,0x2dba244e,0x2fe62ff4,0x1cb62d27,0xad72ab5e,0x2ed02ff4,0x2e1f2f46,0xafafacb0,0xafafaed0,0xa8d52993,0x29342c87,0xac07af6e,0xafbcb000,0xaffcae99,
0xa8d5acb0,0x2875aaaa,0x2e3f2f80,0xa8d5aed0,0x29341648,0x2fed2eb5,0x28142c5d,0x2f302a4e,0x2e992cd8,0x16482d4d,0xa9f19fd9,0x2c872fbc,0x2fff2faf,0xafe6ad27,0xaed0ad27,0xaddca30e,
0xafc9ae99,0xaf80af5a,0x2f462d96,0xafe6ae99,0xaf02afed,0x28d5ab05,0x2fa02ffc,0x230eacd8,0xa934ad27,0x2fbc2f02,0x2c072e3f,0x2ffc2e1f,0x2a4e1cb6,0xa6a12c32,0xa6a12515,0x96482d72,
0xaaaa29f1,0xaed025db,0xacb025db,0x2f801648,0xaf1aaf91,0x2875ae5e,0xae3fafed,0xab5e2d4d,0x2c07a875,0x2b052ff8,0x2d4da17e,0xa814aff4,0x2eb52fc9,0xaf6ead72,0x2dba2fff,0x2eb52e7c,
0x2f022f80,0x2b5e2fe6,0x2b5e2fc9,0x230eaf46,0xacd826a1,0xaf30ad96,0xaf91a9f1,0x2c072fd4,0xad96affc,0x2fdd244e,0xa5dbaee9,0xaf5aad4d,0x2e7c217e,0xad722bb7,0x2fff2d00,0x2fc9217e,
0x2c5da934,0x2f5aa44e,0x30002cd8,0xaeb5adfe,0x2d722ff8,0xacb02d00,0xa7652d00,0x2fff28d5,0xaf02a515,0x217eaf80,0xaf1aaf46,0xaf022765,0xa814af5a,0x2b052fdd,0x2d4da5db,0x2c07ad96,
0xae5eafa0,0xa934aff4,0x2b05abb7,0xaee928d5,0x2eb51cb6,0x2d962ed0,0x2d962fe6,0x2c87ad72,0x27652f6e,0xaf80ac5d,0xaf46a5db,0xa5152f6e,0xaff4ad4d,0x2ff8244e,0xa17eaee9,0xa875affc,
0xad4d2875,0xafbc217e,0xacd8aff8,0x1fd92ff4,0xaa4eafe6,0x2e99aaaa,0x2fd42993,0xaa4eafc9,0x2fff2c87,0xacb02d96,0xa7652d96,0x2d722eb5,0xab5e2c07,0x2875af30,0xae3faf91,0xaf1aacd8,
0x2d962fbc,0x25db2ffc,0xafdda934,0x2f5a2c07,0xafc9a875,0xaaaaafa0,0x2993ad27,0xafe6a875,0x28d5ad72,0x2d002ed0,0x2d002fe6,0x2ff81cb6,0x2d4d2fd4,0xae5ead96,0xafeda9f1,0xaf9126a1,
0x2e1fa765,0x2ff49cb6,0xa8752ddc,0x2e1facb0,0x1fd92f5a,0xafbc25db,0xacd8afdd,0xad4d2d96,0xaeb5aee9,0x2f5aa934,0x30002b05,0x2c5dae5e,0x2f80230e,0xaed02b5e,0xacb02b5e,0xaaaa2f02,
0xacb0afd4,0x9cb6b000,0x2ddc2f5a,0xa765afd4,0x2ff42c07,0x217e2ffc,0xaff8a934,0x28752fbc,0xadfe28d5,0xa44eaff4,0x2cd8abb7,0xa934afa0,0x1648af46,0x25db2fe6,0x25db2fc9,0x29f12f80,
0xafff9648,0xae7ca6a1,0xafc9a6a1,0x2d722a4e,0x2ff81fd9,0x230e2ee9,0x2faf2814,0x217eaf91,0xafeda30e,0x2d4dafa0,0xaf91a8d5,0xae5e2f02,0x2fdd2515,0xb0002aaa,0x2f6e2993,0x2fdda765,
0xa30e2fff,0xad272fc9,0xad272e7c,0x2fafad72,0x2814afdd,0x2ffcaa4e,0x2dfeadba,0xae5ea5db,0xaa4e2f91,0xac5dac07,0xaeb52cd8,0x96482f30,0x2c32af1a,0xa9932ff4,0x2f46abb7,0x2e7caf1a,
0x2fdd1fd9,0x2dba2814,0x2a4e2ee9,0x25dbaf91,0xaf46a8d5,0x2765afaf,0xa515afaf,0xaf802e1f,0x2e3f2c32,0xafa02ddc,0xa17e2fff,0x2e3f2515,0xacd8adba,0x2dfe26a1,0x2934afd4,0x244eaf6e,
0x2814aff8,0x2dfeafaf,0x2ffca30e,0xae5ea17e,0xac872f46,0xaf5a2515,0xaf5aa765,0xa6a12f80,0x2e7cadba,0x1cb62e99,0x2ddc2c5d,0x2fc9adba,0xafaf2b05,0x2f1aaee9,0xab5eae5e,0xad00a934,
0xaf91a30e,0xacd8a8d5,0x2c07afa0,0xaf302f02,0x2dba2c32,0xac5d2fff,0xae992ddc,0x2dba2515,0xa993aeb5,0x2fc9a9f1,0x2fe6a9f1,0x2aaaafdd,0xa17e2fed,0xa30eadfe,0xafaf9fd9,0xaff82c07,
0xaa4e2fed,0xaeb52f91,0xac5dad4d,0x96482e5e,0x2e7cae3f,0x2ddc217e,0x1cb62fa0,0x2fc9ae3f,0xaff82993,0x2bb7afe6,0x2bb7afc9,0xab5eaaaa,0x2f3025db,0xafbc2a4e,0xaee92dba,0xadfe2fdd,
0x2f1a2515,0x2bb72993,0xaff42aaa,0x2f1aa765,0xab05adba,0x2e5eafd4,0x2ee926a1,0x2934af6e,0xa5db2fed,0xadba9fd9,0xaa4eadfe,0xafdd2c07,0x2ddcaf02,0xacb02ff8,0xa7652ff8,0x9cb62e3f,
0x2c32afdd,0x2f46af6e,0xa9933000,0x2e7cafdd,0xafaf2cd8,0xab5ea934,0x2f1aadfe,0xad00a44e,0x2f30217e,0xaee92faf,0xafbc230e,0xadfe2ff8,0xa9f1addc,0x2c5d2765,0x2c5d2cb0,0x2d961cb6,
0xa993aa4e,0x2765ac87,0xa515ac87,0xaaaa2dba,0xafa02f30,0xabb7244e,0xaff42e5e,0x28d51fd9,0x28142bb7,0xaf912e1f,0x1fd92d27,0x2ee9ad00,0x2fd4aed0,0xaf5a2fff,0x3000addc,0x2fd4afe6,
0xafaf2f46,0xafa02e7c,0xafa02c32,0x2d00a993,0x244e2c5d,0xaf913000,0xab052f5a,0x2fbcaeb5,0x3000adfe,0xac872e5e,0x2e99a814,0x2f6eaffc,0x2515ae1f,0x1cb62875,0x2d72aff4,0x2c32ae1f,
0x26a12b05,0xa9f12cd8,0xad962fed,0x2fd4affc,0x2fffae1f,0x2515230e,0x2c32230e,0x2ddcaf1a,0x2875ae7c,0x2d27aaaa,0x2fa0af80,0x2875ac32,0xaee929f1,0x2f91ae99,0x9fd9ac87,0xa8149648,
0x2fedaf1a,0x2f30ae3f,0x29342875,0x2814ab5e,0x26a1addc,0x3000afc9,0x3000ae7c,0xa5db9cb6,0xaed02a4e,0x2f46afd4,0x2993ae99,0xacb02a4e,0xae3f2ffc,0x2d27ae5e,0xae1f2814,0xaf022dfe,
0x9fd9abb7,0x2c07ad27,0x2fedae1f,0xadfe2d00,0xaf6e2cb0,0x25dba993,0x2c5daf46,0xaf6e2ed0,0xaddc2fdd,0xa5159648,0xac329648,0xafff2fd4,0x28d52814,0xabb72934,0xaff42f30,0xafa02fed,
0xb0002ee9,0xae992dfe,0x2c87af30,0xaf6e2fbc,0xac322f02,0xaf802f1a,0xaaaaa17e,0xae7c2f02,0x2b5e1cb6,0xaff42fc9,0xaff42e7c,0xad272ddc,0x2ffcaeb5,0xafed3000,0xacd82f5a,0xab052c5d,
0xa17e2c32,0xad002d72,0xabb71cb6,0xa17e2515,0x2dfea9f1,0xac072c87,0xafed2e99,0x1fd91648,0x2fd4afbc,0xa9f12b05,0xad962f91,0x26a1a44e,0x2aaaae3f,0xa76528d5,0x251528d5,0x2993a875,
0x2fe6aeb5,0x2ddcadba,0xafff2f6e,0x2ed0aeb5,0x2e3fafbc,0x2e1fadfe,0xad272f30,0x2f02aee9,0x1fd9ab5e,0x2e5eae3f,0x244e2875,0x2f30af1a,0xad962993,0x2e99ae7c,0x2e99ac32,0x2f5aaf46,
0x299329f1,0xa76525db,0x251525db,0x2aaa1648,0x28d52934,0xaf02acd8,0x230e244e,0x2fa02dfe,0x28142875,0xaf91aff8,0x1fd9217e,0x2ee92ff4,0x26a12765,0xaa4eaddc,0x16481cb6,0x26a12cb0,
0x2f022f46,0x2b5e2e7c,0x2b5e2c32,0x230ea993,0x2e5e2eb5,0xab051648,0x29342a4e,0x2ee92c5d,0x2d962dfe,0xafddae5e,0x25db2814,0x2f5a2ffc,0x2cb02d27,0xaddcafaf,0x1cb6230e,0x27652d27,
0x2fd42f91,0x2f6e2fed,0x2dba2e5e,0xa6a1ad4d,0x2fff2ff8,0x25152d00,0x2c322d00,0x2ddc28d5,0x2faf2fe6,0xae1fa993,0x28d52aaa,0x2faf2fc9,0x2ee92f5a,0xaf91afdd,0x1fd925db,0x28142d96,
0x2cd82b5e,0x2f912d00,0x2f302faf,0xac07af1a,0x2eb52ddc,0x2d962fc9,0x2d962e7c,0x2c871cb6,0x2fc92f5a,0xa99326a1,0x2aaa2c87,0x2fe62f5a,0x2ff42ffc,0xaff8ae5e,0x217e2814,0x28752dfe,
0x9fd9a875,0x2c07a17e,0x2fed2ff8,0xadfeaff4,0x29f12515,0x2fdd2f46,0x2eb52f80,0x29f1a765,0x2ddc2c87,0x25152d96,0x2c322d96,0x2fff2eb5,0x2fa02ee9,0xaf02ab05,0x230e2934,0x28d52e5e,
0xad96aee9,0xa5dbadfe,0x2fdd2f30,0xaf5aafbc,0xa765abb7,0x2f462b5e,0x2f802ff8,0x2515abb7,0x28d51cb6,0x2d002fc9,0x2d002e7c,0x2ff82ddc,0x2dfe2c5d,0xacd81648,0x244e2a4e,0x29342eb5,
0xaff8afc9,0xae3fafff,0x2f022d72,0xaff8ae7c,0xadfeaf5a,0x2c07a5db,0x2fed2fdd,0x9fd9ad96,0xa6a1ac07,0x2f6e2f91,0x2dba2f30,0x2fd42cd8,0x2aaa230e,0xa7652b5e,0x25152b5e,0x29932f02,
0xae7cac5d,0xafffad96,0x2d7229f1,0xafc9ac5d,0xaff4afbc,0xa17eadfe,0x2ff82f30,0xa875aee9,0xad4daf1a,0x2fed2d00,0x2e5e2faf,0x2f912b5e,0x1648a993,0x25db2e7c,0x25db2c32,0x29f12f46,
0xaddc9648,0xafe6a6a1,0xaed0a6a1,0x2fff2a4e,0xad27affc,0x2d00ac07,0xabb7afbc,0xae1f2934,0x2e5e230e,0x1fd92fa0,0x2f3028d5,0x244eaf02,0x2c872fe6,0xadbaaf46,0x2a4e2f80,0x2c872fc9,
0xa30e2d72,0xad272c32,0xad272515,0x2faf1cb6,0xafbcae99,0x1fd9af6e,0xad4db000,0xacd82c87,0x2a4eab05,0x2c5d2fbc,0x2eb5244e,0x1648af91,0x2ed02fa0,0xaf80ad00,0x2aaa2faf,0x2cb02fa0,
0x2c872ffc,0x16482fbc,0xa9f12c07,0x2e99a934,0xaf80a8d5,0xac32afaf,0xae7cafaf,0xaaaa2e1f,0xa30eaed0,0x2f1a2d72,0x2e1f9cb6,0xa30eafe6,0x2fed2dba,0xaffca6a1,0x2b052fd4,0x2cd82f6e,
0x2fbc2e1f,0x2d4d2f02,0x9fd92e3f,0x2cd8ad27,0xac872993,0xaf5aacb0,0xaf5aaed0,0xa6a12f46,0xacb0b000,0x2fff25db,0x2d72a6a1,0xa765b000,0x2faf2934,0xaf1a2814,0x2b5e2fed,0x2d002f30,
0x2f30230e,0x2fed28d5,0x28142fa0,0x2934af02,0x16482ed0,0xafd41cb6,0xafddad72,0x16482fe6,0xaf46aeb5,0x2ed0a9f1,0x2cb0a9f1,0xa993afdd,0x2e1fa44e,0xad002d4d,0x2bb72ffc,0x2d272ee9,
0x2a4eacd8,0x2eb5ab05,0x2c5d2ffc,0x1648afed,0x2cb02ff4,0xad722d27,0xafffab5e,0x27652ff4,0xaff8aaaa,0x2bb7ae7c,0x2bb7ac32,0xab5eaf80,0x2b05ac87,0xa8142f6e,0x2c073000,0x2d4d2e99,
0xa8d5afe6,0x2875af80,0x2e3f2f46,0xa8d5afc9,0x2f912dba,0xa44e2fd4,0xafbca6a1,0x2b052f6e,0xae99244e,0x9648affc,0x29f1ad4d,0xac87aee9,0x1cb6af02,0x25152ff8,0x2c322ff8,0x2d722e3f,
0xaed0ae99,0xaaaaaf5a,0x2f802d96,0xacb0ae99,0x2faf244e,0x2b5e2f30,0xaf1a1fd9,0x2d002e5e,0xab052d27,0xac07af02,0x2814ae3f,0xad4dae1f,0xa9f1afff,0x2c5d2ed0,0x2c5d2fe6,0x2d962ddc,
0xaf46aa4e,0xac32ac87,0xae7cac87,0x29932dba,0x2f1a2b05,0xa8752fed,0x2e3f2cd8,0x2b5eaffc,0xaee9abb7,0x2f30ae1f,0xadfead27,0xafbc2d00,0x2eb52c32,0xaf6e1cb6,0x2dba2d72,0x2eb52515,
0xafaf2993,0xafa02515,0xafa0a765,0x2d002aaa,0x2feda6a1,0x29342d96,0x2f3029f1,0x2814afd4,0xb0001fd9,0x2c87afed,0xae99ac07,0xaf6e2dfe,0x2fe6217e,0xafff2bb7,0x2ddc2d00,0x2ed0217e,
0xac5d2f30,0xaf5a2e5e,0xb000244e,0x2eb51fd9,0x2ddcae1f,0x2e7c230e,0x2fc9230e,0x1cb6af1a,0xaf022cb0,0x217eaf46,0xaf1aa993,0xaf022ed0,0x2fbca9f1,0xaf302e99,0x2dfe2c87,0x2ee91648,
0x244e2fa0,0xab052ff4,0xaf912bb7,0x2fbca8d5,0x26a1afff,0x3000ac32,0x3000a515,0xa5dbaddc,0xac322f6e,0xaaaaac5d,0xaf80a5db,0xae7c2f6e,0x2e3fadfe,0xad272fed,0x2e1f2c07,0x2f029fd9,
0x2dfe2bb7,0x28142d27,0xae5e2e1f,0x2ffcad00,0xaa4eae7c,0x2e99af80,0x2fd4aaaa,0xaa4eac32,0x9cb62fdd,0xae7c9648,0xafc99648,0xaddc2fd4,0x2b5eafbc,0xa8752f91,0x2e3f2b05,0x2f1aa44e,
0x3000a814,0x2e999fd9,0xac872f91,0x2f6eaee9,0xaed0a875,0x2993afa0,0x2f46ad27,0xacb0a875,0x2b5e2ddc,0xaff42c32,0xaff42515,0xad272fff,0x1fd9afd4,0x244e2d96,0x2e5e29f1,0x2f30a6a1,
0x2e1faed0,0x2ff4addc,0xa8752fff,0x2e1fafe6,0xaffc29f1,0xa814ac87,0x2e5eae99,0xadfe9648,0x2eb52814,0xaf5a2f30,0xb0002934,0xac5d2fed,0xa993ae3f,0x2c3228d5,0x2e7c28d5,0x2f46a875,
0x2515afd4,0x2d72b000,0x1cb62f5a,0x2c32afd4,0xae3f2ee9,0xae1f1fd9,0x2d27af91,0xaf022814,0x2ffca8d5,0xacd82ff4,0xafed2bb7,0xab052fa0,0xad96aaaa,0x2e99a515,0x2e992765,0x2f5aa993,
0x1cb6adba,0x2cb0aeb5,0x2765aeb5,0xaddc2f6e,0xaff82d4d,0xa30ea814,0xafaf2c07,0xa17e2b05,0xa44e2e3f,0xadfe2b5e,0xa9342f1a,0x2cd8a875,0x2fddacb0,0xb0002f80,0x2f6eaaaa,0x2fddaed0,
0xad009cb6,0xa17ea765,0xa17eacb0,0xabb72ddc,0xaee92fdd,0xad4d2a4e,0xaffc2dba,0x244e25db,0x29f12934,0xafd42ee9,0xa6a12e5e,0x2d96ab05,0x2fc9af1a,0xaf462ff4,0x2f80abb7,0x2fe6af1a,
0xafdd2d4d,0xadba2c07,0xaa4ea814,0xa5db2b05,0xaaaa2f1a,0xafc92f02,0xafe62f02,0x2993a17e,0x2e3fa765,0xafa02fff,0xa17e2d72,0x2e3facb0,0x2e5eb000,0xad4d2eb5,0x2f91ac5d,0x2fedaf5a,
0xaee92ff8,0xaffc2faf,0xad4d230e,0x244e217e,0x25db2aaa,0xaf6e2fe6,0xaf6e2fc9,0x2c5da993,0x2fe6adba,0xad722e99,0x1cb62c5d,0x2ed0adba,0x2bb7af30,0xa8d52c07,0x2fa0acd8,0x2ff4af91,
0xa9342e3f,0xae5e2f1a,0xaee92b5e,0x2b05a875,0x2dbaa765,0xac5d2d72,0xae992fff,0x2dbaacb0,0x2f80afd4,0xa7652a4e,0x25152a4e,0x2f46ae99,0x217eacd8,0x230e1fd9,0x2fafad4d,0x2ff8afbc,
0x29f1244e,0xa6a12934,0xafd42dfe,0x2d96acd8,0x2fe6ae3f,0x1cb6217e,0xad722fa0,0x2ed0ae3f,0x2d27af80,0x2875a515,0x28752765,0x2fa0af46,0xa934a5db,0x2c07aa4e,0x2fbcadba,0x2ffcafdd,
0x2f1aacb0,0x2bb7aaaa,0xaff42f80,0x2f1aaed0,0x2f30b000,0x2cd8ac5d,0xac072eb5,0x2f91af5a,0x25dbacd8,0x2dbaad4d,0x2a4e1fd9,0x2fddafbc,0xad722875,0x2e7cae1f,0x2fc9ae1f,0x2fffaff4,
0x2fc9afdd,0x2f80af6e,0xaf463000,0x2fe6afdd,0x2bb7ae5e,0x2fa0af91,0xa8d52d4d,0x2ff4afed,0xa934a17e,0x2fbcafaf,0x2c07a30e,0x2ffcaff8,0xaf5a2d72,0x2fd4afc9,0x2fd4ae7c,0x3000afff,
0x3c003c00,0x3bff3c00,0x3c003c00,0x3bfa3bfd,0x3c003c00,0x3bef3bf5,0x3c003c00,0x3bde3be7,0x3c003c00,0x3bc83bd4,0x3c003c00,0x3bac3bbb,0x3c003c00,0x3b8b3b9d,0x3bff3c00,0x3b653b79,
0x3c003c00,0x3bff3c00,0x3c003c00,0x3bf83bfd,0x3bff3c00,0x3bea3bf2,0x3bff3bff,0x3bd63be1,0x3bfe3bff,0x3bba3bc9,0x3bfd3bfe,0x3b983baa,0x3bfc3bfd,0x3b6f3b84,0x3bfb3bfc,0x3b3f3b58,
0x3c003c00,0x3bff3c00,0x3bff3c00,0x3bf63bfc,0x3bfe3bff,0x3be53bef,0x3bfd3bfe,0x3bcc3bda,0x3bfb3bfc,0x3bab3bbc,0x3bf93bfa,0x3b813b97,0x3bf63bf7,0x3b4f3b69,0x3bf23bf4,0x3b163b33,
0x3c003c00,0x3bff3c00,0x3bff3c00,0x3bf53bfb,0x3bfd3bfe,0x3be03bec,0x3bfa3bfc,0x3bc23bd2,0x3bf63bf8,0x3b9a3baf,0x3bf23bf4,0x3b683b82,0x3bec3bef,0x3b2c3b4b,0x3be53be9,0x3ae83b0b,
0x3c003c00,0x3bfe3c00,0x3bfe3bff,0x3bf23bfa,0x3bfb3bfd,0x3bda3be8,0x3bf63bf9,0x3bb73bca,0x3bf03bf4,0x3b873ba0,0x3be83bed,0x3b4c3b6b,0x3bdf3be4,0x3b073b2b,0x3bd43bda,0x3ab63ae0,
0x3c003c00,0x3bfe3c00,0x3bfd3bff,0x3bf03bf9,0x3bf93bfb,0x3bd43be4,0x3bf23bf6,0x3bab3bc1,0x3be83bed,0x3b733b91,0x3bdd3be3,0x3b2f3b53,0x3bcf3bd6,0x3ade3b08,0x3bbf3bc7,0x3a813ab1,
0x3c003c00,0x3bfe3c00,0x3bfc3bfe,0x3bee3bf8,0x3bf63bf9,0x3bce3be0,0x3bec3bf1,0x3b9e3bb7,0x3bdf3be6,0x3b5e3b80,0x3bcf3bd7,0x3b103b39,0x3bbc3bc6,0x3ab33ae3,0x3ba53bb1,0x3a493a7f,
0x3bff3c00,0x3bfe3c00,0x3bfb3bfe,0x3beb3bf7,0x3bf23bf7,0x3bc63bdb,0x3be53bed,0x3b903bad,0x3bd43bdd,0x3b473b6e,0x3bbf3bca,0x3aee3b1d,0x3ba53bb2,0x3a853abc,0x3b873b97,0x3a0d3a4b,
0x3bfd3c00,0x3bfa3c00,0x3be83bf6,0x3bcc3be9,0x3bbf3bd6,0x3b713ba4,0x3b813ba2,0x3aeb3b33,0x3b2f3b5a,0x3a3d3a99,0x3acb3aff,0x396b39d8,0x3a543a92,0x387a38f6,0x39cd3a13,0x36dd37ee,
0x3bfd3c00,0x3bfa3c00,0x3be53bf4,0x3bc83be7,0x3bb73bd1,0x3b653b9d,0x3b713b97,0x3ad53b22,0x3b163b46,0x3a193a7c,0x3aa53ae0,0x393739ad,0x3a213a65,0x383538ba,0x398b39d8,0x36313753,
0x3bfd3c00,0x3bf93c00,0x3be23bf3,0x3bc33be5,0x3bae3bcb,0x3b593b95,0x3b603b8a,0x3abd3b11,0x3afb3b30,0x39f43a5e,0x3a7e3abf,0x39023980,0x39eb3a37,0x37dd387c,0x3946399b,0x358136b5,
0x3bfc3c00,0x3bf93c00,0x3bdf3bf1,0x3bbf3be3,0x3ba53bc6,0x3b4c3b8c,0x3b4f3b7d,0x3aa53aff,0x3ade3b1a,0x39cd3a3f,0x3a543a9c,0x38cc3951,0x39b33a07,0x374e383d,0x38fd395b,0x34cf3614,
0x3bfc3c00,0x3bf83c00,0x3bdc3bf0,0x3bba3be1,0x3b9c3bc0,0x3b3f3b84,0x3b3d3b70,0x3a8c3aed,0x3ac13b02,0x39a63a1f,0x3a293a78,0x38943922,0x397939d4,0x36bb37f9,0x38b23918,0x341a3570,
0x3bfc3c00,0x3bf83c00,0x3bd83bee,0x3bb53bdf,0x3b923bb9,0x3b323b7b,0x3b2a3b62,0x3a733ad9,0x3aa23ae9,0x397d39fe,0x39fc3a52,0x385a38f1,0x393c399f,0x36253775,0x386538d3,0x32c634c9,
0x3bfb3c00,0x3bf73c00,0x3bd43bed,0x3bb03bdc,0x3b873bb2,0x3b243b72,0x3b163b53,0x3a583ac6,0x3a813ad0,0x395439dc,0x39cd3a2b,0x382038bf,0x38fd3969,0x358d36ee,0x3815388c,0x31533420,
0x3bfb3c00,0x3bf63c00,0x3bd03beb,0x3bab3bda,0x3b7c3bab,0x3b163b69,0x3b013b43,0x3a3d3ab1,0x3a603ab5,0x392939ba,0x399d3a02,0x37c8388c,0x38bc3930,0x34f33665,0x37853842,0x2fbd32ea,
0x3bf63c00,0x3bf03c00,0x3ba53bd7,0x3b733bc1,0x3b073b5f,0x3a813b08,0x3a213a9c,0x392939e1,0x38fd3996,0x36ff385d,0x374e3858,0x327c3529,0x345735da,0xa9b12d1a,0x2cce3191,0xb49fb160,
0x3bf53c00,0x3bef3c00,0x3b9f3bd5,0x3b6c3bbe,0x3af73b55,0x3a6f3afc,0x3a043a87,0x390739c7,0x38d13972,0x36993832,0x36d23822,0x316c34b1,0x3371354c,0xad65297f,0x27763036,0xb552b2b9,
0x3bf53c00,0x3bef3c00,0x3b9a3bd2,0x3b653bbb,0x3ae83b4b,0x3a5c3af0,0x39e73a71,0x38e539ad,0x38a3394d,0x36313807,0x365437d8,0x305b3438,0x323234bd,0xafef1e48,0xa4522db0,0xb602b408,
0x3bf43c00,0x3bee3c00,0x3b943bd0,0x3b5e3bb7,0x3ad83b41,0x3a493ae3,0x39c93a5a,0x38c13992,0x38743927,0x35c837b7,0x35d4376a,0x2e91337d,0x30f0342c,0xb13ba7da,0xac0629e3,0xb6afb4b1,
0x3bf33c00,0x3bed3c00,0x3b8e3bcd,0x3b573bb4,0x3ac73b36,0x3a353ad6,0x39aa3a43,0x389e3976,0x38453900,0x355e375e,0x355236f9,0x2c6a3288,0x2f593334,0xb27cac51,0xaef51a48,0xb759b558,
0x3bf23c00,0x3bec3c00,0x3b873bca,0x3b4f3bb1,0x3ab63b2b,0x3a213ac9,0x398b3a2b,0x387a395b,0x381538d8,0x34f33705,0x34cf3687,0x28843191,0x2cce320d,0xb3baaeaa,0xb0f0a91b,0xb7feb5fd,
0x3bf23c00,0x3beb3c00,0x3b813bc7,0x3b473bad,0x3aa53b20,0x3a0d3abc,0x396b3a13,0x3855393e,0x37c838b0,0x348736aa,0x344b3614,0x16483099,0x288430e4,0xb47bb080,0xb263ad4c,0xb850b69e,
0x3bf13c00,0x3bea3c00,0x3b7a3bc4,0x3b3f3baa,0x3a933b14,0x39f83aae,0x394a39fa,0x38303922,0x37643887,0x341a364e,0x3389359f,0xa81f2f40,0x9cb62f72,0xb517b1aa,0xb3d3b004,0xb89eb73d,
0x3be93c00,0x3be13c00,0x3b373ba6,0x3af13b86,0x39e33aa0,0x392e3a27,0x380a3905,0x3599380d,0x335935f1,0x217f31db,0xac382d4c,0xb546b12e,0xb5b1b2d2,0xb90cb7cd,0xb8eab7d8,0xbadbba0b,
0x3be83c00,0x3be03c00,0x3b2f3ba2,0x3ae83b82,0x39cd3a92,0x39163a17,0x37c838e7,0x354637d8,0x327c3593,0xa4523115,0xae5f2aac,0xb5c8b226,0xb648b3f7,0xb94ab828,0xb933b838,0xbb0aba43,
0x3be73c00,0x3bdf3c00,0x3b273b9e,0x3ade3b7d,0x39b83a83,0x38fd3a07,0x377a38c9,0x34f33796,0x319e3534,0xa9b1304e,0xb042257f,0xb648b31b,0xb6ddb48d,0xb986b867,0xb979b881,0xbb35ba78,
0x3be63c00,0x3bde3c00,0x3b1e3b9b,0x3ad53b79,0x39a13a74,0x38e539f6,0x372c38ab,0x349f3753,0x30be34d5,0xac9c2f0e,0xb153a0b6,0xb6c6b408,0xb76fb51d,0xb9c0b8a6,0xb9bcb8c9,0xbb5cbaaa,
0x3be53c00,0x3bdd3c00,0x3b163b97,0x3acb3b74,0x398b3a65,0x38cc39e5,0x36dd388c,0x344b3710,0x2fbd3475,0xae5f2d7e,0xb263a91b,0xb742b481,0xb7feb5ab,0xb9f8b8e2,0xb9fcb90e,0xbb7fbad9,
0x3be43c00,0x3bdc3c00,0x3b0d3b93,0x3ac13b70,0x39743a56,0x38b239d4,0x368d386d,0x33eb36cc,0x2dfb3414,0xb0102bd9,0xb371ac83,0xb7bdb4f9,0xb845b637,0xba2db91d,0xba39b951,0xbb9ebb05,
0x3be33c00,0x3bda3c00,0x3b043b8f,0x3ab63b6b,0x395d3a47,0x389939c3,0x363c384d,0x33403687,0x2c383365,0xb0f028b6,0xb43eae78,0xb81ab570,0xb889b6c1,0xba60b956,0xba73b992,0xbbb8bb2e,
0x3be23c00,0x3bd93c00,0x3afb3b8a,0x3aac3b67,0x39463a37,0x387f39b1,0x35eb382d,0x32943642,0x28e832a1,0xb1cf2248,0xb4c3b036,0xb855b5e5,0xb8ccb748,0xba90b98d,0xbaa9b9d0,0xbbcfbb53,
0x3c003c00,0x3bfe3c00,0x3c003c00,0x3bf73bfc,0x3c003c00,0x3beb3bf2,0x3c003c00,0x3bd93be3,0x3c003c00,0x3bc13bce,0x3c003c00,0x3ba53bb4,0x3c003c00,0x3b823b94,0x3bff3bff,0x3b5b3b6f,
0x3c003c00,0x3bfe3c00,0x3c003c00,0x3bf53bfb,0x3bff3c00,0x3be63bee,0x3bff3bff,0x3bcf3bdb,0x3bfe3bfe,0x3bb23bc1,0x3bfd3bfe,0x3b8e3ba1,0x3bfc3bfd,0x3b643b7a,0x3bfb3bfb,0x3b333b4c,
0x3c003c00,0x3bfe3c00,0x3bff3c00,0x3bf33bf9,0x3bfe3bff,0x3be03beb,0x3bfd3bfd,0x3bc53bd3,0x3bfb3bfc,0x3ba13bb4,0x3bf83bf9,0x3b753b8c,0x3bf53bf7,0x3b413b5c,0x3bf23bf3,0x3b063b25,
0x3c003c00,0x3bfd3c00,0x3bff3bff,0x3bf03bf8,0x3bfc3bfe,0x3bda3be6,0x3bf93bfb,0x3bb93bca,0x3bf53bf7,0x3b8e3ba5,0x3bf03bf3,0x3b5a3b75,0x3beb3bee,0x3b1c3b3c,0x3be43be7,0x3ad53afa,
0x3c003c00,0x3bfd3c00,0x3bfe3bff,0x3bee3bf7,0x3bfa3bfc,0x3bd33be2,0x3bf53bf8,0x3bac3bc1,0x3bee3bf2,0x3b7a3b94,0x3be63beb,0x3b3c3b5c,0x3bdd3be2,0x3af43b19,0x3bd13bd7,0x3aa13acb,
0x3bff3c00,0x3bfc3c00,0x3bfc3bfe,0x3beb3bf5,0x3bf73bfa,0x3bcb3bdd,0x3bf03bf4,0x3b9e3bb6,0x3be63beb,0x3b643b82,0x3bda3be0,0x3b1c3b41,0x3bcb3bd3,0x3ac83af4,0x3bba3bc3,0x3a683a9a,
0x3bff3c00,0x3bfb3bff,0x3bfb3bfd,0x3be73bf3,0x3bf43bf8,0x3bc33bd7,0x3be93bef,0x3b8f3bab,0x3bdb3be3,0x3b4c3b6f,0x3bca3bd3,0x3afa3b25,0x3bb63bc1,0x3a9a3acb,0x3b9f3bab,0x3a2c3a65,
0x3bff3c00,0x3bfb3bff,0x3bf93bfd,0x3be43bf2,0x3bf03bf5,0x3bba3bd1,0x3be23be9,0x3b7f3b9f,0x3bcf3bd9,0x3b333b5b,0x3bb93bc5,0x3ad53b06,0x3b9e3bac,0x3a683aa1,0x3b7f3b8f,0x39ec3a2c,
0x3bfa3bff,0x3bf33bff,0x3be03bf0,0x3bba3bdc,0x3bb13bcb,0x3b533b8c,0x3b6e3b92,0x3ac33b10,0x3b183b45,0x3a0c3a6c,0x3aaf3ae5,0x393139a3,0x3a343a73,0x383938b9,0x39a939f1,0x36513767,
0x3bf93bff,0x3bf23bfe,0x3bdc3bee,0x3bb43bd9,0x3ba73bc5,0x3b453b82,0x3b5c3b85,0x3aa93afd,0x3afb3b2e,0x39e43a4c,0x3a863ac3,0x38fa3973,0x39fd3a44,0x37e03878,0x396339b2,0x359c36c3,
0x3bf93bff,0x3bf13bfe,0x3bd83beb,0x3bae3bd6,0x3b9d3bbe,0x3b373b78,0x3b493b76,0x3a8f3ae9,0x3add3b16,0x39bb3a2a,0x3a5b3a9f,0x38c03942,0x39c43a12,0x374b3836,0x39193971,0x34e4361d,
0x3bf83bff,0x3bf03bfe,0x3bd33be9,0x3ba73bd3,0x3b923bb6,0x3b273b6e,0x3b353b67,0x3a733ad4,0x3abe3afd,0x39913a08,0x3a2e3a79,0x38853910,0x398839de,0x36b237e6,0x38cd392d,0x34293573,
0x3bf73bff,0x3bee3bfe,0x3bcf3be7,0x3ba13bcf,0x3b873baf,0x3b183b64,0x3b203b57,0x3a573abe,0x3a9d3ae2,0x396539e4,0x39ff3a51,0x384938dc,0x394939a7,0x3617375c,0x387e38e6,0x32d834c6,
0x3bf63bff,0x3bed3bfe,0x3bca3be4,0x3b9a3bcc,0x3b7b3ba6,0x3b073b58,0x3b0a3b47,0x3a3a3aa8,0x3a7b3ac6,0x393939bf,0x39cf3a28,0x380b38a7,0x3908396e,0x357936cf,0x382c389d,0x315a3417,
0x3bf53bff,0x3bec3bfe,0x3bc53be2,0x3b933bc8,0x3b6e3b9e,0x3af73b4d,0x3af43b35,0x3a1c3a91,0x3a573aa9,0x390b399a,0x399c39fd,0x37993871,0x38c53934,0x34d8363f,0x37af3851,0x2fb032cc,
0x3bf43bff,0x3beb3bfe,0x3bbf3bdf,0x3b8c3bc5,0x3b613b95,0x3ae53b41,0x3adc3b23,0x39fd3a79,0x3a323a8b,0x38dc3973,0x396739d1,0x37183839,0x388038f7,0x343535ae,0x37023803,0x2ca93166,
0x3be93bfd,0x3bdd3bfc,0x3b853bc1,0x3b413b9e,0x3ad43b35,0x3a343ac8,0x39de3a61,0x38c53988,0x38ac394b,0x361737e0,0x36963800,0x30863435,0x3322351a,0xaecf2484,0x267b2ffb,0xb590b352,
0x3be83bfd,0x3bdb3bfc,0x3b7d3bbd,0x3b383b99,0x3ac13b29,0x3a1e3ab9,0x39bd3a48,0x389f396a,0x387b3923,0x35a83783,0x3611378e,0x2ecf336b,0x31d53484,0xb0b8a54d,0xa5b22d26,0xb645b45a,
0x3be63bfd,0x3bd93bfc,0x3b753bb9,0x3b2e3b94,0x3aaf3b1c,0x3a083aa9,0x399c3a2e,0x3878394b,0x384938fa,0x35373724,0x358a3718,0x2c903269,0x308633d9,0xb207ab8e,0xac77289d,0xb6f6b508,
0x3be53bfd,0x3bd73bfb,0x3b6d3bb5,0x3b253b8f,0x3a9b3b0f,0x39f13a9a,0x397a3a14,0x3851392d,0x381638cf,0x34c636c3,0x350236a1,0x289d3166,0x2e6b32a7,0xb352ae39,0xaf7ea052,0xb7a4b5b3,
0x3be33bfd,0x3bd53bfb,0x3b653bb0,0x3b1b3b8a,0x3a883b01,0x39d93a8a,0x395739f9,0x3829390d,0x37c538a4,0x34543662,0x34783628,0x12483061,0x2b8e3172,0xb44eb055,0xb141aac5,0xb826b65c,
0x3be23bfd,0x3bd33bfb,0x3b5c3bac,0x3b103b85,0x3a733af4,0x39c13a79,0x393439de,0x380038ed,0x375c3878,0x33c035ff,0x33d935ae,0xa86b2eb6,0x2484303c,0xb4f0b18b,0xb2bfae39,0xb878b702,
0x3be03bfc,0x3bd13bfb,0x3b533ba7,0x3b063b7f,0x3a5f3ae5,0x39a93a68,0x391039c1,0x37af38cd,0x36f1384c,0x32d8359c,0x32bf3531,0xac772ca9,0xa6162e07,0xb590b2bf,0xb41db086,0xb8c8b7a4,
0x3bde3bfc,0x3bcf3bfb,0x3b4b3ba3,0x3afb3b7a,0x3a4a3ad7,0x39913a57,0x38eb39a5,0x375c38ac,0x3684381e,0x31ee3537,0x31a434b4,0xaeb62934,0xac2b2b2a,0xb62eb3f1,0xb4d8b1ee,0xb914b821,
0x3bcd3bfa,0x3bbb3bf8,0x3af03b74,0x3a933b43,0x39783a46,0x38a239b0,0x3707388b,0x344736e0,0x310334d2,0xacdb2e39,0xb07a2052,0xb690b3e5,0xb6c9b490,0xb991b87e,0xb95eb86e,0xbb30ba79,
0x3bcb3bfa,0x3bb93bf8,0x3ae53b6e,0x3a863b3c,0x395e3a34,0x3885399c,0x36b23869,0x33d93696,0x3016346c,0xaeb62c90,0xb197a616,0xb713b472,0xb761b526,0xb9ccb8be,0xb9a5b8b9,0xbb58baad,
0x3bc93bfa,0x3bb63bf8,0x3ada3b68,0x3a793b35,0x39443a22,0x38693988,0x365c3846,0x3322364b,0x2e523405,0xb04829ca,0xb2b3ab2a,0xb793b4f0,0xb7f6b5b9,0xba05b8fc,0xb9e8b901,0xbb7dbadd,
0x3bc73bfa,0x3bb43bf7,0x3acf3b62,0x3a6c3b2e,0x392a3a10,0x384c3973,0x36053824,0x326935ff,0x2c77333a,0xb13424e9,0xb3cdada3,0xb809b56d,0xb844b64b,0xba3cb939,0xba28b947,0xbb9dbb0a,
0x3bc53bf9,0x3bb13bf7,0x3ac33b5c,0x3a5f3b27,0x391039fd,0x382e395e,0x35ae3800,0x31b035b3,0x29343269,0xb21f9f12,0xb472afb0,0xb846b5e8,0xb88bb6da,0xba70b973,0xba65b98a,0xbbb9bb34,
0x3bc23bf9,0x3baf3bf7,0x3ab73b56,0x3a513b20,0x38f539ea,0x38113949,0x355537ba,0x30f63567,0x21e43197,0xb309a839,0xb4fcb0de,0xb883b662,0xb8cfb767,0xbaa1b9ab,0xba9db9ca,0xbbd0bb5a,
0x3bc03bf9,0x3bac3bf7,0x3aab3b50,0x3a443b19,0x38d939d7,0x37e63934,0x34fc3772,0x303c351a,0xa48430c5,0xb3f1ab8e,0xb584b1e2,0xb8beb6da,0xb912b7f1,0xbacfb9e2,0xbad2ba08,0xbbe3bb7c,
0x3bbe3bf9,0x3ba93bf6,0x3a9f3b49,0x3a363b12,0x38be39c4,0x37a9391e,0x34a23729,0x2f0134cc,0xa9fd2fe2,0xb46cad71,0xb60bb2e4,0xb8f7b750,0xb953b83c,0xbafaba16,0xbb03ba42,0xbbf1bb9a,
0x96488000,0xa6ad8000,0x9cb69a48,0xad00aaac,0x9fdb9e48,0xb029aeaa,0xa17fa0b6,0xb1cfb0fd,0xa311a248,0xb371b2a1,0xa452a3db,0xb487b420,0xa51ba4b6,0xb552b4ed,0xa5e4a57f,0xb61ab5b6,
0x9cb68000,0xa7768000,0xa311a0b6,0xad97ab75,0xa5e4a4b6,0xb0a6af72,0xa81fa711,0xb27cb191,0xa94da8b6,0xb426b365,0xaa7aa9e3,0xb50bb499,0xaba7ab11,0xb5ebb57c,0xac6aac1f,0xb6c6b659,
0x9fdb8000,0xa81f8000,0xa5e4a3db,0xae2dac1f,0xa8e8a7da,0xb122b01d,0xaadea9e3,0xb328b226,0xac6aabd9,0xb493b414,0xad65ace7,0xb58db511,0xae5fade2,0xb682b608,0xaf59aedc,0xb76fb6f9,
0xa17f8000,0xa8848000,0xa81fa57f,0xaec3ac83,0xaadea97f,0xb19eb080,0xacceac1f,0xb3d3b2b9,0xae2dad7e,0xb4ffb475,0xaf8baedc,0xb60eb587,0xb074b01d,0xb715b693,0xb122b0cb,0xb80ab796,
0xa3118000,0xa8e88000,0xa94da711,0xaf59ace7,0xac6aab11,0xb219b0e4,0xae2dad4c,0xb43eb34c,0xafefaf0e,0xb56ab4d5,0xb0d7b067,0xb68db5fd,0xb1b6b147,0xb7a6b71b,0xb294b226,0xb85ab817,
0xa4528000,0xa94d8000,0xaa7aa852,0xafefad4c,0xad65ac51,0xb294b147,0xaf8bae78,0xb493b3df,0xb0d7b04e,0xb5d4b534,0xb1e8b160,0xb70ab670,0xb2f7b26f,0xb81ab7a1,0xb402b37d,0xb8a8b862,
0xa51b8000,0xa9b18000,0xaba7a91b,0xb042adb0,0xae5fad1a,0xb30fb1aa,0xb074afa4,0xb4e7b438,0xb1b6b115,0xb63cb593,0xb2f7b257,0xb785b6e3,0xb41ab396,0xb85fb812,0xb4b7b469,0xb8f3b8ab,
0xa5e48000,0xaa168000,0xac6aa9e3,0xb08dae14,0xaf59ade2,0xb389b20d,0xb122b067,0xb53ab481,0xb294b1db,0xb6a4b5f1,0xb402b34c,0xb7feb753,0xb4b7b45d,0xb8a3b852,0xb56ab511,0xb93cb8f1,
0xaa7a8000,0xacce8000,0xb0d7ae78,0xb328b0cb,0xb402b26f,0xb5dfb4bd,0xb58db4c9,0xb805b6f9,0xb70ab64e,0xb902b887,0xb83ab7c2,0xb9e3b976,0xb8e5b891,0xbaa2ba47,0xb982b935,0xbb3abaf3,
0xaade8000,0xad008000,0xb122aedc,0xb371b0fd,0xb43eb2d2,0xb61ab4ed,0xb5dfb511,0xb82ab73d,0xb76fb6aa,0xb92eb8b0,0xb874b817,0xba11b9a4,0xb924b8ce,0xbaceba74,0xb9c5b976,0xbb60bb1d,
0xab438000,0xad338000,0xb16caf40,0xb3bab12e,0xb47bb334,0xb654b51d,0xb631b558,0xb850b780,0xb7d2b705,0xb958b8d8,0xb8adb84d,0xba3db9d0,0xb962b909,0xbaf7baa0,0xba04b9b5,0xbb83bb43,
0xaba78000,0xad658000,0xb1b6afa4,0xb402b160,0xb4b7b396,0xb68db54c,0xb682b59f,0xb874b7c2,0xb81ab75e,0xb982b900,0xb8e5b881,0xba67b9fa,0xb99db943,0xbb1ebac9,0xba41b9f2,0xbba1bb67,
0xac068000,0xad978000,0xb201b004,0xb426b191,0xb4f3b3f7,0xb6c6b57c,0xb6d2b5e5,0xb899b802,0xb84ab7b7,0xb9aab927,0xb91bb8b5,0xba90ba23,0xb9d6b97b,0xbb42baf0,0xba7aba2b,0xbbbcbb86,
0xac388000,0xadc98000,0xb24bb036,0xb44bb1c3,0xb52fb42c,0xb6ffb5ab,0xb721b62b,0xb8bcb822,0xb87ab807,0xb9d2b94d,0xb94fb8e7,0xbab6ba4b,0xba0db9b1,0xbb63bb14,0xbab0ba62,0xbbd2bba2,
0xac6a8000,0xadfb8000,0xb294b067,0xb46fb1f4,0xb56ab45d,0xb737b5da,0xb76fb670,0xb8e0b842,0xb8a8b832,0xb9f8b972,0xb982b918,0xbadbba71,0xba41b9e5,0xbb81bb36,0xbae1ba95,0xbbe3bbbb,
0xac9c8000,0xae2d8000,0xb2deb099,0xb493b226,0xb5a5b48d,0xb76fb608,0xb7bdb6b5,0xb902b862,0xb8d6b85d,0xba1db996,0xb9b3b948,0xbafeba95,0xba73ba17,0xbb9cbb55,0xbb10bac6,0xbbf1bbd0,
0xae5f8000,0xafef8000,0xb4b7b257,0xb5d4b3df,0xb7a6b637,0xb8a8b7a1,0xb924b881,0xba1db96d,0xba41b9ba,0xbb32bab5,0xbb1ebab8,0xbbd6bb93,0xbbb3bb72,0xbbfebbf9,0xbbfabbe1,0xbba9bbe3,
0xae918000,0xb0108000,0xb4dbb288,0xb5f7b408,0xb7ddb665,0xb8c1b7cd,0xb946b8a0,0xba39b989,0xba64b9dc,0xbb4abad0,0xbb3dbad9,0xbbe2bba6,0xbbc8bb8c,0xbbf9bbfe,0xbbffbbee,0xbb8bbbd2,
0xaec38000,0xb0298000,0xb4ffb2b9,0xb61ab420,0xb80ab693,0xb8dbb7f9,0xb966b8bf,0xba54b9a4,0xba85b9fe,0xbb60bae9,0xbb59baf9,0xbbedbbb7,0xbbd9bba4,0xbbf0bc00,0xbc00bbf8,0xbb6abbbe,
0xaef58000,0xb0428000,0xb523b2ea,0xb63cb438,0xb825b6c1,0xb8f3b812,0xb986b8dd,0xba6fb9be,0xbaa5ba1f,0xbb76bb02,0xbb73bb17,0xbbf5bbc7,0xbbe7bbb9,0xbbe4bbff,0xbbfcbbfe,0xbb45bba6,
0xaf278000,0xb05b8000,0xb546b31b,0xb65fb451,0xb840b6ee,0xb90cb828,0xb9a6b8fb,0xba89b9d8,0xbac4ba3f,0xbb89bb1a,0xbb8bbb33,0xbbfbbbd5,0xbbf2bbcb,0xbbd6bbfb,0xbbf4bc00,0xbb1bbb8a,
0xaf598000,0xb0748000,0xb56ab34c,0xb682b469,0xb85ab71b,0xb924b83d,0xb9c5b918,0xbaa2b9f2,0xbae1ba5e,0xbb9cbb30,0xbba1bb4e,0xbbffbbe1,0xbbfabbdb,0xbbc3bbf5,0xbbe7bbfe,0xbaeebb6b,
0xaf8b8000,0xb08d8000,0xb58db37d,0xb6a4b481,0xb874b748,0xb93cb852,0xb9e3b935,0xbababa0b,0xbafeba7c,0xbbacbb46,0xbbb5bb67,0xbc00bbeb,0xbbffbbe8,0xbbaebbec,0xbbd7bbf9,0xbabdbb49,
0xafbd8000,0xb0a68000,0xb5b1b3ae,0xb6c6b499,0xb88eb775,0xb954b867,0xba00b951,0xbad1ba23,0xbb18ba99,0xbbbcbb5a,0xbbc6bb7d,0xbbffbbf3,0xbc00bbf2,0xbb96bbe0,0xbbc2bbf0,0xba89bb22,
0xb0be8000,0xb1858000,0xb6e8b4b1,0xb7f3b570,0xb96bb87c,0xba19b91d,0xbae8ba3b,0xbb7fbae6,0xbbc9bb6e,0xbc00bbdd,0xbbfcbbf9,0xbb8ebbe5,0xbb7abbd1,0xba35bafc,0xba50baf9,0xb820b93e,
0xb0d78000,0xb19e8000,0xb70ab4c9,0xb80ab587,0xb982b891,0xba2db930,0xbafeba52,0xbb8ebaf9,0xbbd6bb80,0xbc00bbe6,0xbbf6bbfd,0xbb76bbda,0xbb5cbbc0,0xba00bad6,0xba15bacc,0xb79bb8fb,
0xb0f08000,0xb1b68000,0xb72cb4e1,0xb81ab59f,0xb999b8a6,0xba41b943,0xbb13ba69,0xbb9cbb0b,0xbbe0bb91,0xbbfebbed,0xbbeebc00,0xbb5cbbcd,0xbb3abbab,0xb9c9baae,0xb9d6ba9c,0xb6f4b8b5,
0xb1098000,0xb1cf8000,0xb74eb4f9,0xb82ab5b6,0xb9afb8ba,0xba54b956,0xbb27ba7f,0xbba9bb1d,0xbbe9bba0,0xbbfbbbf4,0xbbe3bc00,0xbb3fbbbe,0xbb16bb95,0xb990ba83,0xb994ba69,0xb648b86d,
0xb1228000,0xb1e88000,0xb76fb511,0xb83ab5ce,0xb9c5b8ce,0xba67b969,0xbb3aba95,0xbbb5bb2e,0xbbf1bbaf,0xbbf6bbf8,0xbbd7bbfe,0xbb21bbad,0xbaeebb7b,0xb954ba56,0xb94fba33,0xb599b822,
0xb13b8000,0xb2018000,0xb790b529,0xb84ab5e5,0xb9dab8e2,0xba7ab97b,0xbb4cbaaa,0xbbc0bb3e,0xbbf7bbbc,0xbbefbbfc,0xbbc8bbfb,0xbb01bb9b,0xbac4bb5f,0xb916ba27,0xb907b9fa,0xb4e7b7ac,
0xb1538000,0xb2198000,0xb7b2b540,0xb85ab5fd,0xb9f0b8f6,0xba8cb98d,0xbb5ebabf,0xbbcbbb4e,0xbbfcbbc9,0xbbe7bbff,0xbbb7bbf6,0xbadebb86,0xba97bb41,0xb8d6b9f6,0xb8bcb9be,0xb432b710,
0xb16c8000,0xb2328000,0xb7d2b558,0xb86ab614,0xba04b909,0xba9eb99f,0xbb6fbad3,0xbbd4bb5d,0xbbfebbd4,0xbbdebc00,0xbba3bbee,0xbababb70,0xba67bb20,0xb894b9c3,0xb86fb980,0xb2f7b670,
0x98b69248,0xa901a2ad,0x9d7f9bdb,0xadd5ac2b,0xa0529f12,0xb093af7e,0xa1e4a11b,0xb238b166,0xa376a2ad,0xb3d9b309,0xa484a420,0xb4bab454,0xa54da4e9,0xb584b520,0xa616a5b2,0xb64bb5e8,
0x9f1298b6,0xa998a376,0xa420a1e4,0xae84aca9,0xa67ba54d,0xb11cb02f,0xa86ba7a8,0xb2f0b207,0xa998a901,0xb460b3d9,0xaac5aa2f,0xb543b4d2,0xabf2ab5c,0xb622b5b3,0xac90ac44,0xb6fcb690,
0xa1e49bdb,0xaa2fa420,0xa6dfa4e9,0xaf33ad26,0xa966a86b,0xb1a4b09f,0xab5caa61,0xb3a8b2a7,0xaca9ac2b,0xb4d2b454,0xada3ad26,0xb5cbb54f,0xae9dae20,0xb6beb645,0xaf97af1a,0xb7a9b734,
0xa4209d7f,0xaac5a484,0xa8cfa6df,0xafe2ada3,0xab8eaa2f,0xb22cb10f,0xad26ac77,0xb42fb346,0xae84add5,0xb543b4ba,0xafe2af33,0xb651b5cb,0xb09fb048,0xb756b6d4,0xb14db0f6,0xb829b7d5,
0xa54d9f12,0xab5ca4e9,0xaa2fa86b,0xb048ae20,0xacdbabf2,0xb2b3b17f,0xae9dadbc,0xb48ab3e5,0xb02faf7e,0xb5b3b520,0xb10fb09f,0xb6d4b645,0xb1eeb17f,0xb7ebb761,0xb2ccb25d,0xb87bb839,
0xa67ba052,0xabf2a54d,0xab8ea966,0xb09fae9d,0xadeeacdb,0xb33ab1ee,0xb00aaf01,0xb4e4b441,0xb11cb093,0xb622b584,0xb22cb1a4,0xb756b6be,0xb33ab2b3,0xb83eb7eb,0xb423b3c0,0xb8cab885,
0xa7a8a11b,0xac44a5b2,0xac77aa61,0xb0f6af1a,0xaf01adbc,0xb3c0b25d,0xb0c5b023,0xb53db490,0xb207b166,0xb690b5e8,0xb346b2a7,0xb7d5b734,0xb441b3e5,0xb885b839,0xb4deb490,0xb917b8cf,
0xa86ba1e4,0xac90a616,0xad26ab5c,0xb14daf97,0xb00aae9d,0xb423b2cc,0xb17fb0c5,0xb596b4de,0xb2f0b238,0xb6fcb64b,0xb42fb3a8,0xb829b7a9,0xb4e4b48a,0xb8cab87b,0xb596b53d,0xb961b917,
0xacdba67b,0xaf33a8cf,0xb1a4b00a,0xb429b1fa,0xb466b33a,0xb66db54f,0xb5eeb52c,0xb846b783,0xb767b6ad,0xb93db8c5,0xb866b80e,0xba16b9ae,0xb90db8bb,0xbacbba75,0xb9a7b95c,0xbb5abb18,
0xad26a6df,0xaf7ea901,0xb1fab048,0xb454b238,0xb4a8b3a8,0xb6adb584,0xb645b579,0xb86eb7ca,0xb7d0b70d,0xb96ab8f0,0xb8a2b846,0xba44b9db,0xb94eb8fa,0xbaf7baa2,0xb9eab99e,0xbb7ebb40,
0xad71a744,0xafc9a934,0xb251b086,0xb47eb276,0xb4eab40b,0xb6ebb5b9,0xb69bb5c5,0xb895b809,0xb81cb76c,0xb995b919,0xb8dcb87e,0xba70ba08,0xb98cb936,0xbb1fbacd,0xba2ab9de,0xbb9ebb65,
0xadbca7a8,0xb00aa966,0xb2a7b0c5,0xb4a8b2b3,0xb52cb441,0xb729b5ee,0xb6f1b611,0xb8bbb82c,0xb84eb7ca,0xb9bfb942,0xb914b8b4,0xba9aba32,0xb9c8b971,0xbb44baf5,0xba66ba1a,0xbbbabb86,
0xae07a806,0xb02fa998,0xb2fdb103,0xb4d2b2f0,0xb56db478,0xb767b622,0xb745b65c,0xb8e1b84e,0xb880b813,0xb9e8b96a,0xb94bb8e8,0xbac1ba5b,0xba01b9a9,0xbb66bb1b,0xba9fba53,0xbbd1bba3,
0xae52a839,0xb055a9ca,0xb352b141,0xb4fcb32e,0xb5aeb4ae,0xb7a4b656,0xb799b6a7,0xb906b871,0xb8b1b841,0xba10b991,0xb981b91c,0xbae7ba82,0xba38b9e0,0xbb85bb3d,0xbad4ba8a,0xbbe3bbbc,
0xae9da86b,0xb07aa9fd,0xb3a8b17f,0xb526b36b,0xb5eeb4e4,0xb7e0b68a,0xb7ebb6f1,0xb92ab892,0xb8e1b86e,0xba36b9b7,0xb9b4b94e,0xbb0abaa8,0xba6cba14,0xbba0bb5d,0xbb04babc,0xbbf1bbd1,
0xaee8a89d,0xb09faa2f,0xb3fdb1bd,0xb54fb3a8,0xb62eb51a,0xb80eb6be,0xb81eb73a,0xb94eb8b4,0xb910b89a,0xba5bb9db,0xb9e6b97e,0xbb2cbacb,0xba9dba46,0xbbb8bb7b,0xbb31baec,0xbbfbbbe3,
0xb0c5aa61,0xb1eeabf2,0xb579b3e5,0xb6beb4e4,0xb82cb6f1,0xb90db83e,0xb971b8d4,0xba6cb9c8,0xba7fb9ff,0xbb66baf7,0xbb4bbaed,0xbbebbbb8,0xbbcdbb95,0xbbf4bc00,0xbbffbbf0,0xbb80bbca,
0xb0eaaa93,0xb213ac12,0xb5a2b411,0xb6e5b502,0xb849b724,0xb928b856,0xb993b8f5,0xba88b9e4,0xbaa1ba22,0xbb7cbb10,0xbb67bb0d,0xbbf4bbc8,0xbbdebbad,0xbbeabc00,0xbbffbbf9,0xbb5cbbb3,
0xb10faac5,0xb238ac2b,0xb5cbb42f,0xb70db520,0xb866b756,0xb942b86e,0xb9b4b914,0xbaa2b9ff,0xbac1ba44,0xbb90bb29,0xbb81bb2c,0xbbfbbbd6,0xbbebbbc1,0xbbdbbbfc,0xbbfbbbff,0xbb34bb98,
0xb134aaf8,0xb25dac44,0xb5f4b44e,0xb734b53d,0xb883b788,0xb95cb885,0xb9d5b934,0xbabcba1a,0xbae1ba65,0xbba3bb40,0xbb99bb48,0xbbffbbe3,0xbbf6bbd3,0xbbcabbf6,0xbbf2bc00,0xbb07bb7a,
0xb15aab2a,0xb282ac5e,0xb61db46c,0xb75cb55b,0xb89fb7ba,0xb975b89d,0xb9f5b953,0xbad5ba34,0xbafeba84,0xbbb4bb56,0xbbafbb62,0xbc00bbed,0xbbfcbbe2,0xbbb5bbed,0xbbe4bbfd,0xbad7bb57,
0xb17fab5c,0xb2a7ac77,0xb645b48a,0xb783b579,0xb8bbb7eb,0xb98eb8b4,0xba14b971,0xbaedba4e,0xbb1bbaa2,0xbbc3bb6b,0xbbc1bb7b,0xbbffbbf5,0xbc00bbee,0xbb9cbbe1,0xbbd2bbf6,0xbaa2bb31,
0xb1a4ab8e,0xb2ccac90,0xb66db4a8,0xb7a9b596,0xb8d7b80e,0xb9a7b8ca,0xba32b98e,0xbb04ba66,0xbb35bac0,0xbbd1bb7e,0xbbd2bb91,0xbbfbbbfb,0xbbffbbf7,0xbb80bbd2,0xbbbbbbeb,0xba6abb07,
0xb1c9abc0,0xb2f0aca9,0xb696b4c6,0xb7d0b5b3,0xb8f2b826,0xb9bfb8e1,0xba4fb9ab,0xbb1bba7f,0xbb4ebadc,0xbbddbb90,0xbbe0bba6,0xbbf5bbfe,0xbbfcbbfd,0xbb61bbc0,0xbba0bbdd,0xba2ebada,
0xb315acc2,0xb41dad8a,0xb7f6b5d1,0xb890b6b8,0xb9d7b8f7,0xba86b9a0,0xbb30ba96,0xbbb5bb39,0xbbe7bba1,0xbbfabbf6,0xbbecbc00,0xbb4cbbc1,0xbb3fbbab,0xb9bfba9f,0xb9efbaa9,0xb707b8b4,
0xb33aacdb,0xb42fada3,0xb80eb5ee,0xb8a2b6d4,0xb9efb90d,0xba9ab9b4,0xbb44baad,0xbbc1bb4b,0xbbefbbb0,0xbbf5bbfb,0xbbe0bbff,0xbb2dbbaf,0xbb19bb93,0xb983ba72,0xb9abba75,0xb656b869,
0xb35facf4,0xb441adbc,0xb821b60b,0xb8b4b6f1,0xba05b923,0xbaadb9c8,0xbb57bac3,0xbbcdbb5b,0xbbf6bbbe,0xbbeebbfe,0xbbd3bbfd,0xbb0cbb9c,0xbaf0bb78,0xb944ba42,0xb965ba3e,0xb5a2b81c,
0xb383ad0d,0xb454add5,0xb834b628,0xb8c5b70d,0xba1cb939,0xbac0b9db,0xbb69bad9,0xbbd6bb6b,0xbbfbbbcb,0xbbe5bc00,0xbbc2bbf8,0xbae9bb87,0xbac5bb5b,0xb903ba10,0xb91cba03,0xb4eab799,
0xb3a8ad26,0xb466adee,0xb846b645,0xb8d7b729,0xba32b94e,0xbad2b9ef,0xbb7bbaed,0xbbdfbb7a,0xbbfebbd6,0xbbdabc00,0xbbafbbf1,0xbac3bb6f,0xba96bb3b,0xb8c0b9db,0xb8cfb9c6,0xb42fb6f6,
0xb3cdad3f,0xb478ae07,0xb859b662,0xb8e8b745,0xba48b963,0xbae4ba01,0xbb8bbb01,0xbbe7bb88,0xbc00bbe0,0xbbcebbff,0xbb9abbe8,0xba9bbb56,0xba65bb18,0xb87bb9a5,0xb880b985,0xb2e4b651,
0xb3f1ad58,0xb48aae20,0xb86bb67f,0xb8fab761,0xba5db978,0xbaf5ba14,0xbb9abb15,0xbbeebb95,0xbc00bbe9,0xbbc0bbfc,0xbb82bbdd,0xba72bb3b,0xba30baf2,0xb834b96c,0xb82eb942,0xb166b5a8,
0xb40bad71,0xb49cae39,0xb87eb69b,0xb90bb77d,0xba72b98c,0xbb06ba26,0xbba8bb27,0xbbf4bba2,0xbbfebbf0,0xbbb0bbf9,0xbb68bbd0,0xba46bb1d,0xb9f9baca,0xb7d5b931,0xb7b4b8fc,0xafc9b4fc,
0x39b839ba,0x3a973ab5,0x39b339b5,0x3a583a78,0x39af39b1,0x3a153a37,0x39aa39ad,0x39cd39f2,0x39a639a8,0x398239a8,0x39a139a4,0x3933395b,0x399d399f,0x38e03909,0x3999399b,0x388938b5,
0xb979b972,0xb865b832,0xb986b980,0xb8c7b896,0xb994b98d,0xb924b8f6,0xb9a1b99b,0xb97db951,0xb9afb9a8,0xb9d2b9a8,0xb9bcb9b5,0xba21b9fa,0xb9c9b9c3,0xba6bba47,0xb9d6b9d0,0xbab0ba8e,
0xb9f4b9fe,0xbac7bae9,0xb9dfb9e9,0xba7ebaa3,0xb9c9b9d4,0xba2dba56,0xb9b3b9be,0xb9d6ba02,0xb99db9a8,0xb979b9a8,0xb986b992,0xb916b948,0xb970b97b,0xb8adb8e2,0xb958b964,0xb840b877,
0x39373927,0x381a37b7,0x39583948,0x38943858,0x39793969,0x390738ce,0x39993989,0x3974393e,0x39b839a8,0x39da39a8,0x39d639c7,0x3a393a0b,0x39f439e5,0x3a903a65,0x3a113a02,0x3ade3ab8,
0x3a2d3a3f,0x3af43b1a,0x3a093a1b,0x3aa23acc,0x39e339f6,0x3a453a74,0x39bc39d0,0x39df3a13,0x399439a8,0x397039a8,0x396b3980,0x38f83935,0x39413956,0x387a38ba,0x3916392b,0x37e83838,
0xb8f3b8d8,0xb79bb705,0xb929b90e,0xb85fb817,0xb95db943,0xb8eab8a6,0xb990b976,0xb96bb92b,0xb9c0b9a8,0xb9e3b9a8,0xb9f0b9d8,0xba50ba1b,0xba1dba07,0xbab3ba83,0xba49ba33,0xbb0abae0,
0xba64ba7c,0xbb1ebb46,0xba31ba4b,0xbac4baf3,0xb9fcba17,0xba5cba92,0xb9c5b9e1,0xb9e7ba23,0xb98bb9a8,0xb966b9a8,0xb94fb96d,0xb8dbb922,0xb911b930,0xb845b891,0xb8d1b8f1,0xb74eb7ee,
0x38ad3887,0x36ff364e,0x38f838d3,0x382a37ac,0x3941391d,0x38cc387c,0x39863964,0x39623918,0x39c939a8,0x39eb39a8,0x3a0939e9,0x3a673a2b,0x3a453a27,0x3ad53aa0,0x3a7e3a62,0x3b323b05,
0x3b453b6e,0x3bbc3bdd,0x3ae53b17,0x3b573b8f,0x3a733aae,0x3ac73b14,0x39f03a33,0x3a113a71,0x395d39a8,0x393739a8,0x38bc390e,0x384038bf,0x380f3867,0x365f3775,0x36af376a,0x341a3540,
0xb65fb593,0xb389b115,0xb7e8b726,0xb625b4f9,0xb8adb852,0xb830b748,0xb958b905,0xb933b8b5,0xb9f4b9a8,0xba15b9a8,0xba7eba3b,0xbad1ba78,0xbaf4babc,0xbb63bb20,0xbb57bb28,0xbbc6bb9b,
0xbb68bb91,0xbbd0bbed,0xbb04bb39,0xbb6fbba6,0xba89bac9,0xbadbbb2b,0xb9f8ba43,0xba19ba7f,0xb954b9a8,0xb92eb9a8,0xb89eb8fb,0xb820b8ab,0xb7b2b83d,0xb5ebb71b,0xb60eb6e3,0xb2deb4b1,
0x35bc34d5,0x32322f0e,0x377a369e,0x35b13469,0x388e3828,0x380f36ee,0x394f38f1,0x392938a0,0x39fc39a8,0x3a1d39a8,0x3a933a4b,0x3ae53a87,0x3b133ad6,0x3b7a3b36,0x3b783b49,0x3bd93bb1,
0x3b873baf,0x3be13bf8,0x3b213b58,0x3b853bbb,0x3a9e3ae3,0x3aee3b41,0x3a003a52,0x3a213a8e,0x394a39a8,0x392439a8,0x387f38e7,0x37fe3896,0x37423812,0x357636c1,0x356a3659,0x31853420,
0xb517b414,0xb0d7abd9,0xb70ab614,0xb53ab3ae,0xb86fb7f9,0xb7ddb693,0xb946b8dd,0xb91fb88c,0xba04b9a8,0xba25b9a8,0xbaa9ba5a,0xbaf7ba95,0xbb2fbaf0,0xbb90bb4b,0xbb96bb67,0xbbe8bbc4,
0xbba3bbc9,0xbbefbbff,0xbb3dbb74,0xbb9abbcd,0xbab3bafc,0xbb01bb55,0xba09ba62,0xba29ba9c,0xb941b9a8,0xb91bb9a8,0xb85fb8d3,0xb7bdb881,0xb6d2b7cd,0xb4ffb665,0xb4c3b5ce,0xb029b31b,
0x346f32a1,0x2ef52248,0x36993587,0x34c33288,0x385037a1,0x379b3637,0x393c38c9,0x39163877,0x3a0d39a8,0x3a2d39a8,0x3abd3a69,0x3b0a3aa3,0x3b4a3b08,0x3ba33b5f,0x3bb03b82,0x3bf43bd5,
0x3bf83c00,0x3bf93bd4,0x3bac3bdc,0x3be43bfe,0x3b133b69,0x3b543bab,0x3a313aaa,0x3a503ae0,0x391139a8,0x38ea39a8,0x377a386d,0x366b3817,0x34873608,0x313b348d,0x2d9731f4,0xad65291b,
0xac3828b6,0x2ec33365,0xb44bb160,0xb0bea57f,0xb759b5da,0xb648b45d,0xb90cb862,0xb8e5b80d,0xba35b9a8,0xba54b9a8,0xbb1bbab1,0xbb5cbae6,0xbbb5bb72,0xbbe9bbb2,0xbbfcbbe3,0xbbf5bc00,
0xbbfebbfc,0xbbefbbbc,0xbbbdbbe9,0xbbeebc00,0xbb24bb7b,0xbb63bbb9,0xba39bab8,0xba58baed,0xb907b9a8,0xb8e0b9a8,0xb737b858,0xb625b802,0xb40eb5ab,0xb042b42c,0xa9b1b0cb,0x30109a48,
0x25e4ad7e,0xb0beb475,0x33a23036,0x2f8ba3db,0x3715357c,0x360233f7,0x3902384d,0x38db37ee,0x3a3d39a8,0x3a5c39a8,0x3b2c3abf,0x3b6a3af3,0x3bc53b84,0x3bf23bc0,0x3bff3bee,0x3be93c00,
0x3c003bf4,0x3be23ba0,0x3bcc3bf3,0x3bf53bff,0x3b353b8c,0x3b713bc6,0x3a413ac6,0x3a603af9,0x38fd39a8,0x38d639a8,0x36f43842,0x35df37d8,0x3328354c,0x2e913396,0x16482f40,0xb16ca852,
0x251b304e,0x32193534,0xb2adae14,0xad972aac,0xb6d2b51d,0xb5bcb334,0xb8f8b838,0xb8d1b7c2,0xba45b9a8,0xba64b9a8,0xbb3dbacc,0xbb78baff,0xbbd3bb95,0xbbf8bbcb,0xbc00bbf7,0xbbdabbfd,
0xbbfebbe6,0xbbd2bb80,0xbbd9bbfa,0xbbfbbbfb,0xbb45bb9d,0xbb7fbbd1,0xba49bad3,0xba67bb05,0xb8f3b9a8,0xb8ccb9a8,0xb6afb82d,0xb599b7ac,0xb232b4ed,0xac9cb2d2,0x294dace7,0x32c62c83,
0xac06b1db,0xb371b5f1,0x31b62b75,0x2b43adb0,0x368d34bd,0x3576326f,0x38ee3822,0x38c73796,0x3a4d39a8,0x3a6b39a8,0x3b4c3ad9,0x3b853b0b,0x3bdf3ba4,0x3bfd3bd6,0x3bfc3bfd,0x3bc83bf8,
0x3bbd3b5a,0x3b473a99,0x3bfe3bf4,0x3bf93bbe,0x3b8b3bdb,0x3bb83bf7,0x3a6f3b11,0x3a8c3b3e,0x38c139a8,0x389939a8,0x35523780,0x343236cc,0x294d320d,0xad332de2,0xb40eaedc,0xb6a4b408,
0x346336aa,0x36f438b0,0xa6ad3004,0x2e2d3451,0xb52fb1aa,0xb40ead1a,0xb8bcb76a,0xb894b6b5,0xba73b9a8,0xba90b9a8,0xbb92bb17,0xbbbdbb43,0xbbffbbe0,0xbbf6bbf9,0xbbb2bbf0,0xbb35bbb4,
0xbba5bb30,0xbb21ba5e,0xbc00bbeb,0xbbf3bbaa,0xbb98bbe4,0xbbc2bbfb,0xba76bb1d,0xba93bb49,0xb8b7b9a8,0xb88eb9a8,0xb50bb753,0xb3d3b69e,0xa17fb147,0x2f27ac51,0x34b73099,0x37423499,
0xb50bb75e,0xb790b900,0x9cb6b12e,0xb010b4e1,0x34e730e4,0x33892b11,0x38b2373d,0x38893687,0x3a7a39a8,0x3a9739a8,0x3b9e3b22,0x3bc63b4e,0x3c003be8,0x3bef3bfd,0x3b983be5,0x3b0d3b9e,
0x3b893b02,0x3af73a1f,0x3c003bdf,0x3beb3b93,0x3ba33bec,0x3bcb3bfe,0x3a7e3b28,0x3a9b3b53,0x38ad39a8,0x388439a8,0x34c33726,0x33403670,0xa51b3080,0xb08d297f,0xb55eb1c3,0xb7ddb529,
0x35b13807,0x3815394d,0x28843257,0x31093570,0xb49fb01d,0xb2f7a7da,0xb8a8b710,0xb87fb659,0xba81b9a8,0xba9eb9a8,0xbba9bb2e,0xbbcfbb58,0xbbffbbef,0xbbe6bbff,0xbb7abbd7,0xbae1bb86,
0xbb6abad0,0xbacbb9dc,0xbbfdbbd0,0xbbe1bb79,0xbbaebbf2,0xbbd3bc00,0xba85bb33,0xbaa2bb5d,0xb8a3b9a8,0xb87ab9a8,0xb47bb6f9,0xb2adb642,0x2a7aaf72,0x3185a4b6,0x360232ea,0x383a35b6,
0xb654b85d,0xb85fb996,0xac38b37d,0xb201b5fd,0x34572eaa,0x32631e48,0x389e36e3,0x3874362b,0x3a8939a8,0x3aa539a8,0x3bb33b39,0x3bd73b62,0x3bfc3bf5,0x3bdc3c00,0x3b593bc7,0x3ab33b6b,
0x39b739b9,0x3a883aa6,0x39b239b4,0x3a483a68,0x39ae39b0,0x3a033a26,0x39a939ab,0x39bb39e0,0x39a539a7,0x396e3995,0x39a039a3,0x391e3947,0x399c399e,0x38ca38f5,0x3997399a,0x3873389f,
0xb97cb975,0xb87eb84c,0xb98ab983,0xb8deb8ae,0xb997b991,0xb93bb90d,0xb9a5b99e,0xb993b967,0xb9b2b9ab,0xb9e6b9bd,0xb9bfb9b9,0xba34ba0e,0xb9ccb9c6,0xba7dba59,0xb9d9b9d3,0xbac0ba9f,
0xb9efb9f9,0xbab6bad9,0xb9d9b9e4,0xba6aba91,0xb9c4b9cf,0xba18ba42,0xb9aeb9b9,0xb9bfb9ec,0xb997b9a3,0xb961b991,0xb981b98c,0xb8fcb92f,0xb96ab975,0xb892b8c8,0xb953b95e,0xb824b85c,
0x3940392f,0x383937f6,0x39613950,0x38b13876,0x39813971,0x392338eb,0x39a03991,0x398e395a,0x39bf39b0,0x39f339c1,0x39de39cf,0x3a4f3a22,0x39fb39ec,0x3aa43a7b,0x3a183a0a,0x3af03acb,
0x3a243a36,0x3ae13b07,0x39ff3a12,0x3a8b3ab7,0x39d939ec,0x3a2c3a5d,0x39b239c6,0x39c439f9,0x398a399e,0x3953398c,0x39613975,0x38d93917,0x3936394b,0x3859389a,0x390b3921,0x37a43816,
0xb901b8e6,0xb7e6b750,0xb936b91c,0xb883b83c,0xb96ab950,0xb90bb8c8,0xb99cb983,0xb98ab94b,0xb9ccb9b4,0xb9ffb9c6,0xb9fbb9e4,0xba6aba36,0xba28ba12,0xbacaba9b,0xba53ba3e,0xbb1dbaf5,
0xba57ba70,0xbb09bb33,0xba24ba3e,0xbaabbadc,0xb9efba0a,0xba40ba77,0xb9b7b9d3,0xb9c8ba05,0xb97cb99a,0xb944b988,0xb940b95e,0xb8b6b8fe,0xb901b921,0xb81eb86b,0xb8c0b8e1,0xb6fcb79e,
0x38c0389a,0x375636a7,0x390b38e6,0x38543800,0x3953392f,0x38f238a4,0x39973975,0x3985393d,0x39d939b9,0x3a0c39ca,0x3a1839f9,0x3a843a4a,0x3a533a36,0x3aed3abb,0x3a8b3a70,0x3b473b1c,
0x3b2e3b5a,0x3ba63bce,0x3aca3afe,0x3b373b74,0x3a533a91,0x3a9d3aef,0x39cc3a12,0x39de3a42,0x39363983,0x38fc3971,0x389238e6,0x37fb3880,0x37c5383c,0x35d136eb,0x3651370d,0x330934ae,
0xb6c3b5fa,0xb460b251,0xb824b788,0xb6b8b590,0xb8d9b880,0xb873b7d5,0xb981b92f,0xb96eb8f5,0xba18b9cf,0xba48b9e0,0xba9dba5d,0xbafabaa6,0xbb0fbad9,0xbb80bb43,0xbb6cbb40,0xbbd8bbb2,
0xbb51bb7d,0xbbbdbbe0,0xbae7bb1f,0xbb4ebb8c,0xba66baa9,0xbaafbb04,0xb9d1ba1e,0xb9e2ba4e,0xb928b97e,0xb8edb96c,0xb86eb8cd,0xb7afb866,0xb74bb80b,0xb54fb684,0xb5a2b679,0xb197b411,
0x362e3549,0x338330de,0x37e6370d,0x3651350e,0x38c0385c,0x38593788,0x397c3921,0x396a38e6,0x3a2439d3,0x3a5339e4,0x3ab63a70,0x3b0f3ab7,0x3b2e3af5,0x3b973b5a,0x3b8d3b61,0x3be83bc7,
0x3b703b9c,0x3bd03bef,0x3b033b3d,0x3b653ba2,0x3a793ac1,0x3ac03b19,0x39d53a2a,0x39e63a59,0x3919397a,0x38de3967,0x384938b4,0x3761384c,0x36cf37b4,0x34cc361d,0x34f035e2,0x302332e4,
0xb596b496,0xb244aecf,0xb783b690,0xb5e8b48a,0xb8a7b836,0xb83eb73a,0xb978b912,0xb965b8d7,0xba30b9d7,0xba5fb9e8,0xbacdba82,0xbb23bac8,0xbb4cbb10,0xbbacbb6f,0xbbaabb7f,0xbbf4bbd8,
0xbb8dbbb7,0xbbe0bbf9,0xbb1dbb5a,0xbb7abbb5,0xba8bbad9,0xbad0bb2d,0xb9d9ba36,0xb9eaba65,0xb90bb975,0xb8cfb963,0xb824b89a,0xb713b831,0xb651b750,0xb447b5b3,0xb43bb549,0xad58b1a4,
0x34fc33c0,0x31032bc0,0x371e3611,0x357e3405,0x388d3811,0x382436eb,0x39733903,0x396138c8,0x3a3c39db,0x3a6a39ec,0x3ae43a94,0x3b373ad9,0x3b673b2a,0x3bbe3b83,0x3bc33b9a,0x3bfc3be7,
0x3bed3bff,0x3bff3bea,0x3b8d3bc7,0x3bcc3bf5,0x3ae13b40,0x3b1d3b83,0x39ef3a70,0x39ff3a9b,0x38c0395e,0x3883394b,0x36c33816,0x357e3750,0x33833549,0x2e84332e,0x28cf3061,0xb0aca5b2,
0xaf7ea376,0x29663166,0xb514b2fd,0xb2bfad71,0xb809b69b,0xb734b555,0xb95cb8b9,0xb949b87b,0xba75b9f1,0xbaa1ba01,0xbb49bae9,0xbb8bbb25,0xbbcfbb96,0xbbf9bbd2,0xbc00bbf2,0xbbe3bbfe,
0xbbf6bc00,0xbbfcbbda,0xbb9fbbd6,0xbbd8bbfb,0xbaf0bb52,0xbb2cbb92,0xb9f3ba7b,0xba03baa6,0xb8b1b95a,0xb873b947,0xb673b7f6,0xb52cb718,0xb276b4de,0xac5eb251,0x2052ae39,0x321f2bf2,
0x2cf4a806,0xad3fb2d8,0x34a831ee,0x31e22a93,0x37db364b,0x36fc3502,0x395738a9,0x3944386b,0x3a8039f5,0x3aab3a05,0x3b5b3af8,0x3b993b33,0x3bdd3ba7,0x3bfd3bdd,0x3bff3bfa,0x3bd13bf9,
0x3bfd3bfd,0x3bf53bc6,0x3baf3be3,0x3be23bff,0x3b003b64,0x3b393ba0,0x39f73a86,0x3a083ab0,0x38a23955,0x38633942,0x362237bf,0x34d836e0,0x31663472,0x286b3172,0xaaf82b5c,0xb390ae84,
0xa8cf2cf4,0x2fc93423,0xb43bb0de,0xb103a484,0xb7a4b5fa,0xb6c3b4ae,0xb953b89a,0xb940b85c,0xba8bb9f9,0xbab6ba0a,0xbb6cbb07,0xbba6bb40,0xbbe8bbb7,0xbc00bbe7,0xbbfabbff,0xbbbabbf1,
0xbc00bbf6,0xbbebbbae,0xbbbebbed,0xbbebbc00,0xbb0fbb74,0xbb47bbad,0xb9fbba91,0xba0cbabb,0xb892b950,0xb854b93d,0xb5d1b788,0xb484b6a7,0xb055b405,0x9248b093,0x2e6ba484,0x347e3086,
0x98b6afe2,0xb128b4d8,0x339c2f97,0x3023a420,0x376c35a8,0x368a345a,0x394e388b,0x393b384c,0x3a9639fd,0x3ac03a0e,0x3b7c3b16,0x3bb33b4d,0x3bf23bc5,0x3c003bef,0x3bf03c00,0x3ba03be5,
0x3bde3b91,0x3b8a3af7,0x3bf23bff,0x3c003be3,0x3b533bb9,0x3b823bdf,0x3a103ac5,0x3a203aec,0x38443939,0x38033925,0x342f366d,0x31b03584,0xa8392f65,0xb15a1d7f,0xb531b1c9,0xb7e0b55b,
0x3269358a,0x35a83819,0xae842a61,0x205231e2,0xb651b405,0xb567b15a,0xb936b83c,0xb923b7f6,0xbacaba12,0xbaf0ba22,0xbbbebb5a,0xbbe3bb88,0xbbfdbbf5,0xbbddbc00,0xbb81bbd6,0xbadfbb7c,
0xbbcebb70,0xbb6dbac6,0xbbf8bbfb,0xbbffbbd6,0xbb60bbc4,0xbb8dbbe7,0xba14bacf,0xba24baf5,0xb834b934,0xb7e6b921,0xb3b4b634,0xb103b549,0x2c44ada3,0x326925b2,0x35e23309,0x384135f4,
0xb3a8b63a,0xb63fb869,0x2cc2ad58,0xa89db2f0,0x3617335f,0x352c30ac,0x3931382c,0x391e37d5,0x3ad43a16,0x3afa3a26,0x3bc93b66,0x3bea3b92,0x3bf93bfa,0x3bcf3bff,0x3b5f3bc5,0x3aad3b5d,
0x3bba3b4c,0x3b4d3a93,0x3bfc3bf6,0x3bfd3bc7,0x3b6c3bce,0x3b973bed,0x3a183ad9,0x3a283afe,0x3824392f,0x37c5391c,0x330935fa,0x3055350e,0xae6b2bc0,0xb377aa61,0xb690b423,0xb890b68a,
0x347236e5,0x36d438b6,0xa9fd2f7e,0x2c1233fd,0xb5dcb2b3,0xb4f0affb,0xb92db81c,0xb919b7b4,0xbaddba1a,0xbb03ba2a,0xbbd3bb72,0xbbf0bb9c,0xbbf2bbfe,0xbbbfbbfc,0xbb38bbaf,0xba77bb3c,
0xbba4bb23,0xbb2aba5b,0xbbffbbee,0xbbfabbb6,0xbb77bbd7,0xbba1bbf3,0xba1cbae2,0xba2cbb07,0xb813b92a,0xb7a4b917,0xb25db5bf,0xaf4cb4d2,0x3048a839,0x34412cf4,0x373a34c0,0x38dc371e,
0xb50eb78e,0xb767b901,0x24e9b0d1,0xadd5b484,0x35a23207,0x34b42e9d,0x3928380b,0x39143793,0x3ae73a1e,0x3b0c3a2e,0x3bdb3b7d,0x3bf53ba6,0x3be93c00,0x3bad3bf7,0x3b0d3b97,0x3a3e3b18,
0xb999b996,0xb889b85d,0xb99db99b,0xb8e0b8b5,0xb9a1b99f,0xb933b909,0xb9a6b9a4,0xb982b95b,0xb9aab9a8,0xb9cdb9a8,0xb9afb9ad,0xba15b9f2,0xb9b3b9b1,0xba58ba37,0xb9b8b9b5,0xba97ba78,
0xb9d6b9dc,0xbab0bad0,0xb9c9b9d0,0xba6bba8e,0xb9bcb9c3,0xba21ba47,0xb9afb9b5,0xb9d2b9fa,0xb9a1b9a8,0xb97db9a8,0xb994b99b,0xb924b951,0xb986b98d,0xb8c7b8f6,0xb979b980,0xb865b896,
0x3958394d,0x38403807,0x39703964,0x38ad3877,0x3986397b,0x391638e2,0x399d3992,0x39793948,0x39b339a8,0x39d639a8,0x39c939be,0x3a2d3a02,0x39df39d4,0x3a7e3a56,0x39f439e9,0x3ac73aa3,
0x3a113a1f,0x3ade3b02,0x39f43a02,0x3a903ab8,0x39d639e5,0x3a393a65,0x39b839c7,0x39da3a0b,0x399939a8,0x397439a8,0x39793989,0x3907393e,0x39583969,0x389438ce,0x39373948,0x381a3858,
0xb916b900,0xb7e8b75e,0xb941b92b,0xb87ab838,0xb96bb956,0xb8f8b8ba,0xb994b980,0xb970b935,0xb9bcb9a8,0xb9dfb9a8,0xb9e3b9d0,0xba45ba13,0xba09b9f6,0xbaa2ba74,0xba2dba1b,0xbaf4bacc,
0xba49ba5e,0xbb0abb30,0xba1dba33,0xbab3bae0,0xb9f0ba07,0xba50ba83,0xb9c0b9d8,0xb9e3ba1b,0xb990b9a8,0xb96bb9a8,0xb95db976,0xb8eab92b,0xb929b943,0xb85fb8a6,0xb8f3b90e,0xb79bb817,
0x38d138b0,0x374e36aa,0x391138f1,0x384537ee,0x394f3930,0x38db3891,0x398b396d,0x39663922,0x39c539a8,0x39e739a8,0x39fc39e1,0x3a5c3a23,0x3a313a17,0x3ac43a92,0x3a643a4b,0x3b1e3af3,
0x3a7e3a99,0x3b323b5a,0x3a453a62,0x3ad53b05,0x3a093a27,0x3a673aa0,0x39c939e9,0x39eb3a2b,0x398639a8,0x396239a8,0x39413964,0x38cc3918,0x38f8391d,0x382a387c,0x38ad38d3,0x36ff37ac,
0xb6afb5f1,0xb41ab1db,0xb80fb76a,0xb65fb540,0xb8bcb867,0xb840b775,0xb95db90e,0xb937b8bf,0xb9f0b9a8,0xba11b9a8,0xba73ba33,0xbac7ba71,0xbae5baae,0xbb57bb14,0xbb45bb17,0xbbbcbb8f,
0xbb57bb80,0xbbc6bbe6,0xbaf4bb28,0xbb63bb9b,0xba7ebabc,0xbad1bb20,0xb9f4ba3b,0xba15ba78,0xb958b9a8,0xb933b9a8,0xb8adb905,0xb830b8b5,0xb7e8b852,0xb625b748,0xb65fb726,0xb389b4f9,
0x360e3534,0x32de304e,0x37b236e3,0x35eb34b1,0x389e383d,0x3820371b,0x395438fb,0x392e38ab,0x39f839a8,0x3a1939a8,0x3a893a43,0x3adb3a7f,0x3b043ac9,0x3b6f3b2b,0x3b683b39,0x3bd03ba6,
0x3b783ba0,0x3bd93bf4,0x3b133b49,0x3b7a3bb1,0x3a933ad6,0x3ae53b36,0x39fc3a4b,0x3a1d3a87,0x394f39a8,0x392939a8,0x388e38f1,0x380f38a0,0x377a3828,0x35b136ee,0x35bc369e,0x32323469,
0xb56ab475,0xb185ad7e,0xb742b659,0xb576b420,0xb87fb812,0xb7feb6c1,0xb94ab8e7,0xb924b896,0xba00b9a8,0xba21b9a8,0xba9eba52,0xbaeeba8e,0xbb21bae3,0xbb85bb41,0xbb87bb58,0xbbe1bbbb,
0xbb96bbbc,0xbbe8bbfc,0xbb2fbb67,0xbb90bbc4,0xbaa9baf0,0xbaf7bb4b,0xba04ba5a,0xba25ba95,0xb946b9a8,0xb91fb9a8,0xb86fb8dd,0xb7ddb88c,0xb70ab7f9,0xb53ab693,0xb517b614,0xb0d7b3ae,
0x34c33365,0x302928b6,0x36d235ce,0x34ff331b,0x385f37cd,0x37bd3665,0x394138d3,0x391b3881,0x3a0939a8,0x3a2939a8,0x3ab33a62,0x3b013a9c,0x3b3d3afc,0x3b9a3b55,0x3ba33b74,0x3bef3bcd,
0x3bb03bd4,0x3bf43c00,0x3b4a3b82,0x3ba33bd5,0x3abd3b08,0x3b0a3b5f,0x3a0d3a69,0x3a2d3aa3,0x393c39a8,0x391639a8,0x385038c9,0x379b3877,0x369937a1,0x34c33637,0x346f3587,0x2ef53288,
0xad972248,0x2d6532a1,0xb487b1f4,0xb13ba91b,0xb77ab608,0xb66bb48d,0xb911b86d,0xb8eab817,0xba31b9a8,0xba50b9a8,0xbb13baaa,0xbb54bae0,0xbbacbb69,0xbbe4bbab,0xbbf8bbdc,0xbbf9bbfe,
0xbbfcbbff,0xbbf5bbc9,0xbbb5bbe3,0xbbe9bc00,0xbb1bbb72,0xbb5cbbb2,0xba35bab1,0xba54bae6,0xb90cb9a8,0xb8e5b9a8,0xb759b862,0xb648b80d,0xb44bb5da,0xb0beb45d,0xac38b160,0x2ec3a57f,
0x29b1abd9,0xb010b414,0x340e30cb,0x30421a48,0x373735ab,0x3625342c,0x39073858,0x38e03802,0x3a3939a8,0x3a5839a8,0x3b243ab8,0x3b633aed,0x3bbd3b7b,0x3bee3bb9,0x3bfe3be9,0x3bef3c00,
0x3bff3bf8,0x3be93baf,0x3bc53bee,0x3bf23c00,0x3b2c3b84,0x3b6a3bc0,0x3a3d3abf,0x3a5c3af3,0x390239a8,0x38db39a8,0x3715384d,0x360237ee,0x33a2357c,0x2f8b33f7,0x25e43036,0xb0bea3db,
0x96482f0e,0x316c34d5,0xb328af40,0xae912852,0xb6f4b54c,0xb5dfb396,0xb8fdb842,0xb8d6b7d8,0xba41b9a8,0xba60b9a8,0xbb35bac6,0xbb71baf9,0xbbccbb8c,0xbbf5bbc6,0xbc00bbf3,0xbbe2bbff,
0xbc00bbed,0xbbdabb91,0xbbd3bbf7,0xbbf8bbfd,0xbb3dbb95,0xbb78bbcb,0xba45bacc,0xba64baff,0xb8f8b9a8,0xb8d1b9a8,0xb6d2b838,0xb5bcb7c2,0xb2adb51d,0xad97b334,0x251bae14,0x32192aac,
0xa94db115,0xb2c6b593,0x32322ce7,0x2c9cac83,0x36af34ed,0x359932d2,0x38f3382d,0x38cc37ac,0x3a4939a8,0x3a6739a8,0x3b453ad3,0x3b7f3b05,0x3bd93b9d,0x3bfb3bd1,0x3bfe3bfa,0x3bd23bfb,
0x3bfc3bdd,0x3bc83b6e,0x3bdf3bfd,0x3bfd3bf8,0x3b4c3ba4,0x3b853bd6,0x3a4d3ad9,0x3a6b3b0b,0x38ee39a8,0x38c739a8,0x368d3822,0x35763796,0x31b634bd,0x2b43326f,0xac062b75,0xb371adb0,
0x340e364e,0x36a43887,0xa94d2edc,0x2d333408,0xb552b20d,0xb432ade2,0xb8c1b780,0xb899b6cc,0xba6fb9a8,0xba8cb9a8,0xbb8bbb11,0xbbb8bb3e,0xbbfebbdb,0xbbf9bbf7,0xbbbdbbf4,0xbb47bbbe,
0xbbb2bb46,0xbb35ba7c,0xbbffbbf0,0xbbf6bbb4,0xbb92bbe0,0xbbbdbbf9,0xba73bb17,0xba90bb43,0xb8bcb9a8,0xb894b9a8,0xb52fb76a,0xb40eb6b5,0xa6adb1aa,0x2e2dad1a,0x34633004,0x36f43451,
0xb4b7b705,0xb742b8d8,0x217fb099,0xaf27b499,0x350b3147,0x33d32c51,0x38b73753,0x388e369e,0x3a7639a8,0x3a9339a8,0x3b983b1d,0x3bc23b49,0x3c003be4,0x3bf33bfb,0x3ba53beb,0x3b213baa,
0x3b983b1a,0x3b0d3a3f,0x3c003be5,0x3bef3b9e,0x3b9e3be8,0x3bc63bfd,0x3a7a3b22,0x3a973b4e,0x38b239a8,0x388939a8,0x34e7373d,0x33893687,0x9cb630e4,0xb0102b11,0xb50bb12e,0xb790b4e1,
0x355e37b7,0x37dd3927,0x251b31c3,0x308d3529,0xb4c3b080,0xb340a97f,0xb8adb726,0xb884b670,0xba7eb9a8,0xba9bb9a8,0xbba3bb28,0xbbcbbb53,0xbc00bbec,0xbbebbbfe,0xbb89bbdf,0xbaf7bb93,
0xbb7abae9,0xbae1b9fe,0xbbffbbd7,0xbbe6bb86,0xbba9bbef,0xbbcfbbff,0xba81bb2e,0xba9ebb58,0xb8a8b9a8,0xb87fb9a8,0xb49fb710,0xb2f7b659,0x2884b01d,0x3109a7da,0x35b13257,0x38153570,
0xb602b832,0xb83ab972,0xaa7ab2ea,0xb185b5b6,0x347b2f72,0x32ad24b6,0x38a336f9,0x387a3642,0x3a8539a8,0x3aa239a8,0x3bae3b33,0x3bd33b5d,0x3bfd3bf2,0x3be13c00,0x3b6a3bd0,0x3acb3b79,
0x3b593ab5,0x3ab339ba,0x3bfc3bc7,0x3bdc3b6b,0x3bb33bf5,0x3bd73c00,0x3a893b39,0x3aa53b62,0x389e39a8,0x387439a8,0x345736e3,0x3263362b,0xac382eaa,0xb2011e48,0xb654b37d,0xb85fb5fd,
0xb99ab997,0xb89fb873,0xb99eb99c,0xb8f5b8ca,0xb9a3b9a0,0xb947b91e,0xb9a7b9a5,0xb995b96e,0xb9abb9a9,0xb9e0b9bb,0xb9b0b9ae,0xba26ba03,0xb9b4b9b2,0xba68ba48,0xb9b9b9b7,0xbaa6ba88,
0xb9d3b9d9,0xba9fbac0,0xb9c6b9cc,0xba59ba7d,0xb9b9b9bf,0xba0eba34,0xb9abb9b2,0xb9bdb9e6,0xb99eb9a5,0xb967b993,0xb991b997,0xb90db93b,0xb983b98a,0xb8aeb8de,0xb975b97c,0xb84cb87e,
0x395e3953,0x385c3824,0x3975396a,0x38c83892,0x398c3981,0x392f38fc,0x39a33997,0x39913961,0x39b939ae,0x39ec39bf,0x39cf39c4,0x3a423a18,0x39e439d9,0x3a913a6a,0x39f939ef,0x3ad93ab6,
0x3a0a3a18,0x3acb3af0,0x39ec39fb,0x3a7b3aa4,0x39cf39de,0x3a223a4f,0x39b039bf,0x39c139f3,0x399139a0,0x395a398e,0x39713981,0x38eb3923,0x39503961,0x387638b1,0x392f3940,0x37f63839,
0xb921b90b,0xb816b7a4,0xb94bb936,0xb89ab859,0xb975b961,0xb917b8d9,0xb99eb98a,0xb98cb953,0xb9c6b9b2,0xb9f9b9c4,0xb9ecb9d9,0xba5dba2c,0xba12b9ff,0xbab7ba8b,0xba36ba24,0xbb07bae1,
0xba3eba53,0xbaf5bb1d,0xba12ba28,0xba9bbaca,0xb9e4b9fb,0xba36ba6a,0xb9b4b9cc,0xb9c6b9ff,0xb983b99c,0xb94bb98a,0xb950b96a,0xb8c8b90b,0xb91cb936,0xb83cb883,0xb8e6b901,0xb750b7e6,
0x38e138c0,0x379e36fc,0x39213901,0x386b381e,0x395e3940,0x38fe38b6,0x399a397c,0x39883944,0x39d339b7,0x3a0539c8,0x3a0a39ef,0x3a773a40,0x3a3e3a24,0x3adc3aab,0x3a703a57,0x3b333b09,
0x3a703a8b,0x3b1c3b47,0x3a363a53,0x3abb3aed,0x39f93a18,0x3a4a3a84,0x39b939d9,0x39ca3a0c,0x39753997,0x393d3985,0x392f3953,0x38a438f2,0x38e6390b,0x38003854,0x389a38c0,0x36a73756,
0xb70db651,0xb4aeb309,0xb83cb7c5,0xb6ebb5d1,0xb8e6b892,0xb880b7fb,0xb983b936,0xb971b8fc,0xba12b9cc,0xba42b9de,0xba91ba53,0xbaefba9d,0xbafebaca,0xbb74bb37,0xbb5abb2e,0xbbcebba6,
0xbb40bb6c,0xbbb2bbd8,0xbad9bb0f,0xbb43bb80,0xba5dba9d,0xbaa6bafa,0xb9cfba18,0xb9e0ba48,0xb92fb981,0xb8f5b96e,0xb880b8d9,0xb7d5b873,0xb788b824,0xb590b6b8,0xb5fab6c3,0xb251b460,
0x367935a2,0x34113197,0x380b374b,0x3684354f,0x38cd386e,0x386637af,0x397e3928,0x396c38ed,0x3a1e39d1,0x3a4e39e2,0x3aa93a66,0x3b043aaf,0x3b1f3ae7,0x3b8c3b4e,0x3b7d3b51,0x3be03bbd,
0x3b613b8d,0x3bc73be8,0x3af53b2e,0x3b5a3b97,0x3a703ab6,0x3ab73b0f,0x39d33a24,0x39e43a53,0x3921397c,0x38e6396a,0x385c38c0,0x37883859,0x370d37e6,0x350e3651,0x3549362e,0x30de3383,
0xb5e2b4f0,0xb2e4b023,0xb7b4b6cf,0xb61db4cc,0xb8b4b849,0xb84cb761,0xb97ab919,0xb967b8de,0xba2ab9d5,0xba59b9e6,0xbac1ba79,0xbb19bac0,0xbb3dbb03,0xbba2bb65,0xbb9cbb70,0xbbefbbd0,
0xbb7fbbaa,0xbbd8bbf4,0xbb10bb4c,0xbb6fbbac,0xba82bacd,0xbac8bb23,0xb9d7ba30,0xb9e8ba5f,0xb912b978,0xb8d7b965,0xb836b8a7,0xb73ab83e,0xb690b783,0xb48ab5e8,0xb496b596,0xaecfb244,
0x3549343b,0x31a42d58,0x37503651,0x35b33447,0x389a3824,0x38313713,0x3975390b,0x396338cf,0x3a3639d9,0x3a6539ea,0x3ad93a8b,0x3b2d3ad0,0x3b5a3b1d,0x3bb53b7a,0x3bb73b8d,0x3bf93be0,
0x3b9a3bc3,0x3be73bfc,0x3b2a3b67,0x3b833bbe,0x3a943ae4,0x3ad93b37,0x39db3a3c,0x39ec3a6a,0x39033973,0x38c83961,0x3811388d,0x36eb3824,0x3611371e,0x3405357e,0x33c034fc,0x2bc03103,
0xb061a8cf,0x25b230ac,0xb549b383,0xb32eae84,0xb816b6c3,0xb750b57e,0xb95eb8c0,0xb94bb883,0xba70b9ef,0xba9bb9ff,0xbb40bae1,0xbb83bb1d,0xbbc7bb8d,0xbbf5bbcc,0xbbffbbed,0xbbeabbff,
0xbbf2bc00,0xbbfebbe3,0xbb96bbcf,0xbbd2bbf9,0xbae9bb49,0xbb25bb8b,0xb9f1ba75,0xba01baa1,0xb8b9b95c,0xb87bb949,0xb69bb809,0xb555b734,0xb2fdb514,0xad71b2bf,0xa376af7e,0x31662966,
0x2e39a052,0xabf2b21f,0x34de3276,0x32512c5e,0x37f63673,0x3718352c,0x395a38b1,0x39473873,0x3a7b39f3,0x3aa63a03,0x3b523af0,0x3b923b2c,0x3bd63b9f,0x3bfb3bd8,0x3c003bf6,0x3bda3bfc,
0x3bfa3bff,0x3bf93bd1,0x3ba73bdd,0x3bdd3bfd,0x3af83b5b,0x3b333b99,0x39f53a80,0x3a053aab,0x38a93957,0x386b3944,0x364b37db,0x350236fc,0x31ee34a8,0x2a9331e2,0xa8062cf4,0xb2d8ad3f,
0xab5c2af8,0x2e843390,0xb472b166,0xb172a86b,0xb7bfb622,0xb6e0b4d8,0xb955b8a2,0xb942b863,0xba86b9f7,0xbab0ba08,0xbb64bb00,0xbba0bb39,0xbbe3bbaf,0xbbffbbe2,0xbbfdbbfd,0xbbc6bbf5,
0xbbffbbfa,0xbbf1bbba,0xbbb7bbe8,0xbbe7bc00,0xbb07bb6c,0xbb40bba6,0xb9f9ba8b,0xba0abab6,0xb89ab953,0xb85cb940,0xb5fab7a4,0xb4aeb6c3,0xb0deb43b,0xa484b103,0x2cf4a8cf,0x34232fc9,
0x2484ae6b,0xb086b47e,0x34053055,0x30931248,0x378835d1,0x36a73484,0x39503892,0x393d3854,0x3a9139fb,0x3abb3a0c,0x3b743b0f,0x3bad3b47,0x3bed3bbe,0x3c003beb,0x3bf63c00,0x3bae3beb,
0x3c003bf0,0x3be53ba0,0x3bc53bf2,0x3bef3c00,0x3b163b7c,0x3b4d3bb3,0x39fd3a96,0x3a0e3ac0,0x388b394e,0x384c393b,0x35a8376c,0x345a368a,0x2f97339c,0xa4203023,0xafe298b6,0xb4d8b128,
0x31c93531,0x355b37e0,0xaf652839,0x9d7f315a,0xb66db42f,0xb584b1b0,0xb939b844,0xb925b803,0xbac5ba10,0xbaecba20,0xbbb9bb53,0xbbdfbb82,0xbbffbbf2,0xbbe3bc00,0xbb91bbde,0xbaf7bb8a,
0xbbd6bb81,0xbb7cbadf,0xbbf5bbfd,0xbc00bbdd,0xbb5abbbe,0xbb88bbe3,0xba12baca,0xba22baf0,0xb83cb936,0xb7f6b923,0xb405b651,0xb15ab567,0x2a61ae84,0x31e22052,0x358a3269,0x381935a8,
0xb309b5e2,0xb5f4b841,0x2da3ac44,0xa5b2b269,0x363433b4,0x35493103,0x39343834,0x392137e6,0x3acf3a14,0x3af53a24,0x3bc43b60,0x3be73b8d,0x3bfb3bf8,0x3bd63bff,0x3b703bce,0x3ac63b6d,
0x3bc53b5f,0x3b5d3aad,0x3bfa3bf9,0x3bff3bcf,0x3b663bc9,0x3b923bea,0x3a163ad4,0x3a263afa,0x382c3931,0x37d5391e,0x335f3617,0x30ac352c,0xad582cc2,0xb2f0a89d,0xb63ab3a8,0xb869b63f,
0x34233690,0x368a3890,0xabc02e6b,0x2a613377,0xb5fab309,0xb50eb055,0xb92fb824,0xb91cb7c5,0xbad9ba18,0xbafeba28,0xbbcebb6c,0xbbedbb97,0xbbf6bbfc,0xbbc7bbfd,0xbb4cbbba,0xba93bb4d,
0xbbafbb38,0xbb3cba77,0xbbfebbf2,0xbbfcbbbf,0xbb72bbd3,0xbb9cbbf0,0xba1abadd,0xba2abb03,0xb81cb92d,0xb7b4b919,0xb2b3b5dc,0xaffbb4f0,0x2f7ea9fd,0x33fd2c12,0x36e53472,0x38b636d4,
0xb4c0b73a,0xb71eb8dc,0x2839b048,0xacf4b441,0x35bf325d,0x34d22f4c,0x392a3813,0x391737a4,0x3ae23a1c,0x3b073a2c,0x3bd73b77,0x3bf33ba1,0x3bee3bff,0x3bb63bfa,0x3b233ba4,0x3a5b3b2a,
0x3b973b0d,0x3b183a3e,0x3c003be9,0x3bf73bad,0x3b7d3bdb,0x3ba63bf5,0x3a1e3ae7,0x3a2e3b0c,0x380b3928,0x37933914,0x320735a2,0x2e9d34b4,0xb0d124e9,0xb484add5,0xb78eb50e,0xb901b767,
0xb97239ba,0x39dc3996,0xb8323ab5,0x3ad0385d,0x3927b9fe,0xba1fb94d,0x37b7bae9,0xbb02b807,0xb8d83a3f,0x3a5e3900,0xb7053b1a,0x3b30375e,0x3887ba7c,0xba99b8b0,0x364ebb46,0xbb5ab6aa,
0xb90039dc,0x3a3f3972,0xad7e3be6,0x3bf83115,0x3807ba99,0xbae9b887,0xabd9bc00,0xbbfca248,0xb5f13b30,0x3b6e3705,0x32a13bed,0x3bd4b04e,0x3365bba0,0xbbc9b4d5,0xb593bbaf,0xbb803475,
0xb88739fe,0x3a99394d,0x35f13bbc,0x3b6eb414,0x3593bb1a,0xbb80b75e,0xb8b0bb02,0xba7c37b7,0xaf0e3bc9,0x3bf43365,0x3a1f39dc,0x3927b972,0xb04ebc00,0xbbed2248,0xbb30b85d,0xb7053ab5,
0xb8073a1f,0x3ae93927,0x39fe3a3f,0x394db900,0x31dbbb80,0xbbddb593,0xbb6eb832,0xb5f13ad0,0x31153c00,0x3be62248,0x3bff32a1,0x28b6bbd4,0xb7b7bb91,0xbb023534,0xbba0304e,0x34d53bed,
0xb7053a3f,0x3b303900,0x3bbc375e,0x3414bb1a,0x2248bbc9,0xbc00b365,0xbbdda8b6,0x31db3bff,0x36aa3bd4,0x3b46b2a1,0x3a7cb64e,0xb8b0bb5a,0xba1fba5e,0xb92738d8,0xb7b739fe,0x3b02394d,
0xb5f13a5e,0x3b6e38d8,0x3bd42bd9,0xb2a1bbfc,0xb115bbf4,0xbbe6af0e,0xb9dc375e,0x39723b1a,0x39273b46,0x3a1fb6aa,0x3475bad0,0xbbafb832,0xbb91b887,0xb5343a99,0x34143c00,0x3bbc2248,
0xb4d53a7c,0x3ba038b0,0x3a3fb593,0xb900bb80,0xb534bc00,0xbb912248,0xb4143ab5,0x3bbc385d,0x3a993a5e,0x3887b8d8,0xb5f1bbfc,0xbb6e2bd9,0xbbffb475,0x28b63baf,0x3ad03a1f,0x3832b927,
0xb3653a99,0x3bc93887,0x36aab996,0xbb46b9ba,0xb7b7bbed,0xbb02304e,0x34d53bfc,0x3ba02bd9,0x3b913927,0x3534ba1f,0xbae9ba3f,0xb8073900,0xbb5a28b6,0x364e3bff,0x3bd43115,0xb2a1bbe6,
0xb1153ab5,0x3be6385d,0xa8b6bb6e,0xbbffb5f1,0xb900bbbc,0xba3f3414,0x3a1f3b30,0x3927b705,0x3bfc375e,0x2bd9bb1a,0xbbedb475,0x304e3baf,0xb9ba3593,0x39963b80,0x3887b832,0xba99bad0,
0xad7e3ad0,0x3bf83832,0xb7b7bbff,0xbb0228b6,0xb9febb6e,0xb94d35f1,0x3bed3887,0x304eba99,0x3bd43414,0xb2a1bbbc,0xb9963534,0x39ba3b91,0xb6aa3900,0x3b463a3f,0xb115bba0,0xbbe6b4d5,
0xa2483ae9,0x3c003807,0xba99bb30,0xb8873705,0xbad0bb02,0xb83237b7,0x3b462d7e,0xb6aabbf8,0x3b1a28b6,0xb75ebbff,0xaf0e3a7c,0x3bf438b0,0xabd93ab5,0x3bfc385d,0xba5ebb5a,0xb8d8364e,
0x2bd93b02,0x3bfc37b7,0xbbedb927,0xb04e3a1f,0xbb6eba7c,0xb5f138b0,0x385db6aa,0xbab5bb46,0x39dcb1db,0xb972bbdd,0x38323c00,0x3ad02248,0x34d53bbc,0x3ba03414,0xbbf4b705,0x2f0e3b30,
0x304e3b1a,0x3bed375e,0xbb91b475,0x35343baf,0xbbd4b9dc,0xb2a13972,0x2248ba7c,0xbc00b8b0,0x3832b64e,0xbad0bb5a,0x3b803a99,0x3593b887,0x39003bfc,0x3a3fabd9,0xb9273414,0x3a1f3bbc,
0x32a13b30,0x3bd43705,0xb996304e,0x39ba3bed,0xbbffb927,0xa8b63a1f,0xb832bbf4,0xbad0af0e,0x3475b8b0,0xbbafba7c,0x3ba03593,0xb4d5bb80,0x3ae93b6e,0x3807b5f1,0x2bd93a99,0x3bfc3887,
0x34753b46,0x3baf36aa,0xb4d53832,0x3ba03ad0,0xbbedb85d,0x304e3ab5,0xbb30bb5a,0xb705364e,0x2248b9fe,0xbc00b94d,0x3887b414,0xba99bbbc,0x3be63a1f,0x3115b927,0x39dc3bf4,0x3972af0e,
0x35933b5a,0x3b80364e,0x31153a99,0x3be63887,0xbba0b705,0x34d53b30,0xbbf4b8d8,0x2f0e3a5e,0xb414bb02,0xbbbcb7b7,0xabd9ba1f,0xbbfcb927,0x3bd43832,0xb2a1bad0,0x3c003972,0xa248b9dc,
0x36aa3b6e,0x3b4635f1,0x38b03bdd,0x3a7c31db,0xbb1ab534,0x375e3b91,0xba3fb04e,0x39003bed,0xb807bbaf,0xbae9b475,0xb94dbbf8,0xb9fead7e,0x3ab53365,0xb85dbbc9,0x39ba28b6,0xb996bbff,
0x37b73b80,0x3b023593,0x3b1a3bc9,0x375eb365,0xba5eb2a1,0x38d83bd4,0xb53435f1,0x3b913b6e,0xb9babbfc,0xb996abd9,0xbbddbae9,0xb1db3807,0x38b0ad7e,0xba7cbbf8,0x28b6b900,0xbbffba3f,
0x385d3b91,0x3ab53534,0x3c003a5e,0x2248b8d8,0xb972ad7e,0x39dc3bf8,0x33653a3f,0x3bc93900,0xbb02bbe6,0xb7b73115,0xbb1ab6aa,0x375e3b46,0x3414b64e,0xbbbcbb5a,0xb94dbbdd,0xb9feb1db,
0x38d83ba0,0x3a5e34d5,0x3b3037b7,0xb705bb02,0xb85d28b6,0x3ab53bff,0x39ba3be6,0x39963115,0xbbc9bb6e,0xb36535f1,0xb6aa31db,0x3b463bdd,0xaf0eb94d,0xbbf4b9fe,0xbbf8bae9,0xad7e3807,
0x394d3baf,0x39fe3475,0x38d82d7e,0xba5ebbf8,0xb64e3115,0x3b5a3be6,0x3bd43b80,0x32a1b593,0xbbffba99,0x28b63887,0x336539ba,0x3bc93996,0xb75ebae9,0xbb1ab807,0xba3fb534,0x39003b91,
0x39ba3bbc,0x39963414,0x31dbb534,0xbbddbb91,0xb3653475,0x3bc93baf,0x3b803927,0xb593ba1f,0xbba0b972,0x34d539dc,0x3a3f3be6,0x39003115,0xb9febbd4,0xb94db2a1,0xb04e35f1,0x3bed3b6e,
0x3a1f3bc9,0x39273365,0xb475b972,0xbbafb9dc,0xabd9364e,0x3bfc3b5a,0x38d831db,0xba5ebbdd,0xbab5b807,0x385d3ae9,0x3c003b30,0x2248b705,0xbb80bbf4,0xb5932f0e,0x38b03b1a,0x3a7c375e,
0x3a7c3bd4,0x38b032a1,0xb972bb5a,0xb9dcb64e,0x2f0e3807,0x3bf43ae9,0x2d7eb534,0xbbf8bb91,0xb94db4d5,0x39fe3ba0,0x3a5e37b7,0xb8d8bb02,0xbc00bb46,0x224836aa,0x3bdd3bc9,0x31dbb365,
0x3ad03bdd,0x383231db,0xbb80bc00,0xb5932248,0x347538d8,0x3baf3a5e,0xb75eb9fe,0xbb1ab94d,0xb705ad7e,0x3b303bf8,0x3414af0e,0xbbbcbbf4,0xbb6eb9dc,0x35f13972,0x3ab538b0,0xb85dba7c,
0x3b1a3be6,0x375e3115,0xbbf4bb46,0x2f0e36aa,0x37053996,0x3b3039ba,0xbae9bbd4,0xb807b2a1,0xb1db304e,0x3bdd3bed,0xb64eb94d,0xbb5ab9fe,0xb9dcb7b7,0x39723b02,0x3365ad7e,0xbbc9bbf8,
0x3b5a3bed,0x364e304e,0xbab5b94d,0x385d39fe,0x38b03a3f,0x3a7c3900,0xbbffbba0,0x28b634d5,0x2d7e3593,0x3bf83b80,0xbb02bbc9,0xb7b7b365,0xb705b1db,0x3b303bdd,0xb807b9ba,0xbae9b996,
0x3b913bf4,0x35342f0e,0xb807b4d5,0x3ae93ba0,0x39ba3ad0,0x39963832,0xba99b972,0x388739dc,0x3593385d,0x3b803ab5,0xbbe6bb6e,0x311535f1,0xad7e304e,0x3bf83bed,0xbbafbbfc,0xb475abd9,
0x3bbc3bf8,0x34142d7e,0xabd92f0e,0x3bfc3bf4,0x3a993b46,0x388736aa,0xb64eb365,0x3b5a3bc9,0x38b039ba,0x3a7c3996,0xb972b85d,0x39dc3ab5,0x34753705,0x3baf3b30,0xbb1aba5e,0x375e38d8,
0x3bdd3bfc,0x31db2bd9,0x364e3807,0x3b5a3ae9,0x3b463ba0,0x36aa34d5,0x31153475,0x3be63baf,0x3a3f3ad0,0x39003832,0xad7e28b6,0x3bf83bff,0x38d83996,0x3a5e39ba,0xb534b2a1,0x3b913bd4,
0x3bf43bff,0x2f0e28b6,0x3a1f3a7c,0x392738b0,0x3bbc3bdd,0x341431db,0x394d39ba,0x39fe3996,0x3b5a3b91,0x364e3534,0x385d38d8,0x3ab53a5e,0x3ad03b1a,0x3832375e,0x36aa37b7,0x3b463b02,
0x3bff3c00,0x28b62248,0x3bc93bd4,0x336532a1,0x3bf83bfc,0x2d7e2bd9,0x3baf3bbc,0x34753414,0x3bed3bf4,0x304e2f0e,0x3b913ba0,0x353434d5,0x3bdd3be6,0x31db3115,0x3b6e3b80,0x35f13593,
0xb5933b6e,0x3b8035f1,0xb1153bdd,0x3be631db,0x34d5bb91,0xbba0b534,0x2f0ebbed,0xbbf4b04e,0xb4143baf,0x3bbc3475,0xabd93bf8,0x3bfc2d7e,0x32a1bbc9,0xbbd4b365,0x2248bbff,0xbc00a8b6,
0x37b73b46,0x3b02b6aa,0x3b1a3832,0x375ebad0,0xb8d8bab5,0xba5e385d,0xbb91b64e,0xb5343b5a,0x39ba39fe,0x3996b94d,0x3bdd3414,0x31dbbbbc,0xba7cb927,0xb8b03a1f,0xbbffaf0e,0xa8b63bf4,
0x3bd43534,0x32a1bb91,0x39bab8d8,0xb996ba5e,0xbbffad7e,0x28b63bf8,0xb8323a3f,0x3ad03900,0x3bafb115,0xb475bbe6,0x34d5bb46,0xbba0b6aa,0xbae9364e,0x38073b5a,0xabd93bdd,0x3bfc31db,
0x3a5eb75e,0xb8d8bb1a,0xb705bbaf,0xbb303475,0xb85d39dc,0x3ab53972,0x39ba3a7c,0x3996b8b0,0x3365bb5a,0xbbc9b64e,0xbb46b887,0xb6aa3a99,0x2f0e3bfc,0x3bf42bd9,0x3bf83414,0x2d7ebbbc,
0x2bd9bbaf,0xbbfcb475,0xbbedad7e,0x304e3bf8,0x35f13be6,0x3b6eb115,0x3ab5b593,0xb85dbb80,0xb9dcba99,0xb9723887,0xb83239ba,0x3ad03996,0x3ba03807,0x34d5bae9,0x2f0ebb91,0xbbf4b534,
0xb9babae9,0xb9963807,0xb1db3b30,0x3bdd3705,0x3bc937b7,0x3365bb02,0xb593bbf8,0xbb802d7e,0xbba028b6,0x34d53bff,0x3a3f3a7c,0x3900b8b0,0x394db85d,0xb9febab5,0xbbedb64e,0xb04e3b5a,
0xbbf8b365,0x2d7e3bc9,0x3b0239dc,0x37b7b972,0x39feb64e,0xb94dbb5a,0xbbedb1db,0x304e3bdd,0xb2a13ae9,0x3bd43807,0x39bab705,0xb996bb30,0xb6aabbf4,0xbb462f0e,0xb1153b1a,0x3be6375e,
0xb8b0385d,0x3a7c3ab5,0x39dcb5f1,0xb972bb6e,0xaf0ebbbc,0xbbf4b414,0xad7e3b30,0x3bf83705,0x39fe3b1a,0x394db75e,0xb8d8bbaf,0xba5e3475,0xbc00b593,0x22483b80,0x3bdd3832,0x31dbbad0,
0x33653bdd,0x3bc931db,0xb6aabc00,0xbb462248,0xbb02ba5e,0xb7b738d8,0x3ba0394d,0x34d5b9fe,0x3b912d7e,0xb534bbf8,0xbae92f0e,0x38073bf4,0xb64e3972,0x3b5a39dc,0x32a1ba7c,0xbbd4b8b0,
0x3b1a3a7c,0x375eb8b0,0xbbf4b593,0x2f0e3b80,0xbb30a248,0x37053c00,0x3807b85d,0xbae9bab5,0x31dbba5e,0xbbddb8d8,0x364e3bfc,0x3b5a2bd9,0x39723baf,0x39dcb475,0xbbc9b927,0xb3653a1f,
0x3b6e304e,0xb5f1bbed,0xb2a139fe,0x3bd4394d,0xb1153a3f,0x3be63900,0xb9dcbba0,0xb97234d5,0xba1fbb80,0xb9273593,0x3baf3365,0xb475bbc9,0x3b9131db,0xb534bbdd,0xb41439ba,0x3bbc3996,
0x3534b900,0xbb91ba3f,0x3ae93b1a,0x3807b75e,0x39ba3bc9,0x3996b365,0xba9928b6,0x38873bff,0xbb80b2a1,0x35933bd4,0xb115bb5a,0xbbe6b64e,0x2d7eba5e,0xbbf8b8d8,0x3baf39fe,0x3475b94d,
0xb807bbf8,0xbae9ad7e,0x39feaf0e,0xb94dbbf4,0x3bdd36aa,0xb1dbbb46,0x35f13bc9,0x3b6e3365,0xb11539ba,0x3be63996,0xbbffb85d,0x28b63ab5,0xbb02bb30,0xb7b73705,0x34d5b8d8,0xbba0ba5e,
0xbbddb9fe,0xb1db394d,0xb64ebbbc,0xbb5ab414,0x36aab75e,0xbb46bb1a,0x3be637b7,0xb115bb02,0x3a3f3bc9,0x3900b365,0xad7e39dc,0x3bf83972,0xba5ea248,0x38d83c00,0xbb91bab5,0xb534385d,
0xba3fa8b6,0x39003bff,0xbbf8b8b0,0x2d7e3a7c,0xb807bbdd,0xbae9b1db,0x2bd9b9ba,0xbbfcb996,0x3b6e3534,0xb5f1bb91,0x3bd43a5e,0x32a1b8d8,0x33653b1a,0x3bc9375e,0xb59337b7,0x3b803b02,
0xa8b63996,0x3bff39ba,0xb365385d,0x3bc93ab5,0xbbf8b9fe,0xad7e394d,0xbbafbae9,0xb4753807,0x304eb900,0xbbedba3f,0x3534b75e,0xbb91bb1a,0x3bdd3a7c,0x31dbb8b0,0x3b6e3b46,0x35f1b6aa,
0x39dc3c00,0x3972a248,0x3ad03bd4,0x3832b2a1,0xb9272bd9,0x3a1f3bfc,0xb7b73414,0x3b023bbc,0xba5ebbf4,0xb8d82f0e,0xbb30bba0,0xb70534d5,0x3887b115,0xba99bbe6,0x364eb593,0xbb5abb80,
0x3bf43972,0xaf0eb9dc,0x3a1f3115,0xb927bbe6,0x34143a99,0x3bbc3887,0x39fe3c00,0x394d2248,0xbb5ab705,0x364e3b30,0xb85d304e,0x3ab53bed,0xb832bba0,0xbad0b4d5,0xbb46bbaf,0xb6aa3475,
0x3887abd9,0xba99bbfc,0xb5f1bae9,0xbb6eb807,0x3b803ba0,0x3593b4d5,0x3a7c3475,0xb8b0bbaf,0xaf0e3832,0x3bf43ad0,0x3a1f3bff,0x392728b6,0xbbedb996,0x304e39ba,0xb70532a1,0x3b303bd4,
0xb414ba1f,0xbbbcb927,0xbbfcba3f,0x2bd93900,0x3a993593,0xb887bb80,0xb64ebad0,0xbb5ab832,0x3a7c3c00,0x38b02248,0x39dc32a1,0xb972bbd4,0xb4753534,0x3baf3b91,0x3b1a3bed,0x375eb04e,
0xbb30bbf4,0xb7052f0e,0xb41434d5,0x3bbc3ba0,0x2248b832,0xbc00bad0,0xbbddb9dc,0x31db3972,0x3b46385d,0xb6aabab5,0xb8b0bb6e,0xba7cb5f1,0x3a1f3bed,0x3927304e,0x37b7abd9,0xbb02bbfc,
0xbb5ab8d8,0x364e3a5e,0x3ab53bfc,0x385d2bd9,0xba7cbbf4,0xb8b0af0e,0xa8b6375e,0x3bff3b1a,0x2d7eb6aa,0xbbf8bb46,0xbb02b832,0x37b73ad0,0x3b303887,0xb705ba99,0xbae9bc00,0xb807a248,
0xb4d53115,0x3ba03be6,0x3a3f36aa,0xb900bb46,0xbb91b996,0x353439ba,0x3bbc3bd4,0x3414b2a1,0xba99bbed,0xb887b04e,0x35f139fe,0x3b6e394d,0xa8b6b7b7,0xbbffbb02,0xb832ad7e,0x3ad03bf8,
0x38323a99,0x3ad03887,0xb593b996,0xbb80b9ba,0xb475304e,0x3baf3bed,0x375e2bd9,0xbb1abbfc,0xbb30b927,0x37053a1f,0x3bbc3a3f,0xb414b900,0xbb6ebbff,0xb5f128b6,0x3ab53be6,0x385d3115,
0x3be63bd4,0x3115b2a1,0xbbffbb5a,0x28b6364e,0x39003ae9,0x3a3f3807,0xba1fbb91,0xb927b534,0xabd934d5,0x3bfc3ba0,0xb04eb7b7,0xbbedbb02,0xb9bab6aa,0x39963b46,0x38873365,0xba99bbc9,
0x3a1f3832,0xb927bad0,0xb47528b6,0x3baf3bff,0x3bfc3b6e,0xabd9b5f1,0xba5eb887,0x38d83a99,0x3ab53bbc,0x385d3414,0xbc00bb91,0x22483534,0x35933900,0x3b803a3f,0xba7cbba0,0xb8b0b4d5,
0x2248b414,0xbc00bbbc,0x3a993b91,0x38873534,0x38323475,0xbad0bbaf,0x36aa3927,0x3b463a1f,0x3b1a39dc,0xb75eb972,0xaf0e3115,0x3bf43be6,0x3bfc3bd4,0x2bd9b2a1,0xb8d8b5f1,0x3a5e3b6e,
0xb9febb02,0xb94db7b7,0x3a5e3927,0xb8d8ba1f,0xb64eb8b0,0xbb5aba7c,0x3bd43b46,0xb2a1b6aa,0x28b6b1db,0xbbffbbdd,0x3bc93c00,0x33652248,0x375e3414,0xbb1abbbc,0x3a3f3b30,0x39003705,
0xbbedbba0,0x304e34d5,0xb534b7b7,0xbb91bb02,0xbbd4bbff,0xb2a1a8b6,0x2248b115,0xbc00bbe6,0xbad0bb6e,0xb832b5f1,0x359331db,0xbb80bbdd,0xb900b9fe,0xba3fb94d,0x39273807,0xba1fbae9,
0xb85db705,0x3ab53b30,0xbc00bbed,0x2248304e,0xb9dcb927,0x39723a1f,0xbbc9bbf4,0xb365af0e,0xbb02ba7c,0x37b738b0,0xbb1abb80,0xb75eb593,0xbbbcbb6e,0x341435f1,0xb9feba99,0xb94db887,
0x34753593,0x3baf3b80,0xb4d5b365,0x3ba03bc9,0x304e32a1,0x3bed3bd4,0xb705b5f1,0x3b303b6e,0xa2482bd9,0x3c003bfc,0xb887b807,0x3a993ae9,0xb115ad7e,0x3be63bf8,0xb972b900,0x39dc3a3f,
0x3b463b5a,0x36aa364e,0x3a7c3a99,0x38b03887,0x3b1a3b30,0x375e3705,0x3a3f3a5e,0x390038d8,0x3ae93b02,0x380737b7,0x39fe3a1f,0x394d3927,0x3ab53ad0,0x385d3832,0x39ba39dc,0x39963972,
0x28b63c00,0x3bffa248,0x33653bd4,0x3bc9b2a1,0xad7ebbfc,0xbbf82bd9,0xb475bbbc,0xbbaf3414,0x304e3bf4,0x3bedaf0e,0x35343ba0,0x3b91b4d5,0xb1dbbbe6,0xbbdd3115,0xb5f1bb80,0xbb6e3593,
0x3bf4a8b6,0xaf0ebbff,0x3a1fb8b0,0xb927ba7c,0xbbbc31db,0x34143bdd,0xb94d3996,0x39fe39ba,0x3b5ab534,0xb64ebb91,0x385dba5e,0xbab5b8d8,0xbad0375e,0x38323b1a,0xb6aa3b02,0x3b4637b7,
0xb1dbbbfc,0xbbdd2bd9,0xbb5ab807,0xb64e3ae9,0x36aa3ba0,0x3b46b4d5,0x3be63475,0x3115bbaf,0xb900bad0,0xba3f3832,0xbbf8a8b6,0x2d7e3bff,0x3a5e3996,0x38d8b9ba,0x3b91b2a1,0xb534bbd4,
0xbbbc2d7e,0x34143bf8,0x2bd93bf4,0x3bfc2f0e,0x3a99b6aa,0xb887bb46,0xb64ebbc9,0xbb5a3365,0xb8b03996,0x3a7c39ba,0x39723ab5,0x39dcb85d,0x3475bb30,0xbbafb705,0xbb1ab8d8,0xb75e3a5e,
0x35343bf4,0x3b91af0e,0x3ae9b4d5,0xb807bba0,0xb996bad0,0xb9ba3832,0xb8873972,0x3a9939dc,0x3b80385d,0x3593bab5,0x3115bb6e,0xbbe6b5f1,0xbbf8b04e,0x2d7e3bed,0x34753bfc,0x3bafabd9,
0x3b5ab04e,0xb64ebbed,0xbab5b9fe,0xb85d394d,0xb8b03900,0x3a7c3a3f,0x3bff34d5,0x28b6bba0,0x2d7ebb80,0xbbf8b593,0xbb023365,0x37b73bc9,0x37053bdd,0x3b30b1db,0x3807b996,0xbae9b9ba,
0xb75ebbe6,0xbb1a3115,0xaf0e3b46,0x3bf436aa,0x3b303996,0x3705b9ba,0xb807bbd4,0xbae932a1,0xbbddb04e,0x31db3bed,0x3b5a394d,0x364eb9fe,0x3972b7b7,0xb9dcbb02,0xbbc9ad7e,0x33653bf8,
0xbad031db,0x38323bdd,0x3b802248,0xb593bc00,0x3475ba5e,0xbbafb8d8,0xb75e394d,0x3b1a39fe,0x37053bf8,0x3b30ad7e,0xb414bbf4,0xbbbcaf0e,0xbb6eb972,0xb5f139dc,0x3ab53a7c,0x385db8b0,
0x38b03bd4,0x3a7cb2a1,0xb9dcbb5a,0xb972364e,0xbbf4b807,0xaf0e3ae9,0x3bf83534,0xad7ebb91,0x39feb4d5,0xb94dbba0,0xb8d837b7,0x3a5e3b02,0xa2483b46,0x3c0036aa,0xb1dbbbc9,0xbbddb365,
0x3a1fb365,0xb927bbc9,0xb47539dc,0x3baf3972,0x2bd93b5a,0x3bfc364e,0xb8d8bbdd,0xba5e31db,0xbab5bae9,0xb85d3807,0x3c003705,0xa248bb30,0x3b802f0e,0xb593bbf4,0xb8b0375e,0x3a7c3b1a,
0xb996bbbc,0xb9ba3414,0x3bdd3534,0xb1dbbb91,0x3bc93475,0xb365bbaf,0xb5933927,0x3b803a1f,0xb4d53972,0x3ba039dc,0xb900bbe6,0xba3f3115,0xb94dbbd4,0xb9fe32a1,0x3bed35f1,0xb04ebb6e,
0xb94d3475,0x39fe3baf,0xb8d8bbf8,0xba5e2d7e,0xb64ebbe6,0xbb5ab115,0x3bd43593,0xb2a1bb80,0x3bff3887,0x28b6ba99,0xb3653996,0x3bc939ba,0xb75e3807,0x3b1a3ae9,0xba3fbb91,0xb9003534,
0x3a5e3ba0,0x38d8b4d5,0xb70537b7,0x3b303b02,0xbab5a8b6,0x385d3bff,0xb996bbe6,0xb9ba3115,0xb365bb6e,0xbbc9b5f1,0x3b4631db,0xb6aabbdd,0x3bf4394d,0x2f0eb9fe,0x2d7e3ae9,0x3bf83807,
0x385db534,0xbab5bb91,0x3c0038d8,0xa248ba5e,0x39723bf8,0x39dcad7e,0xb3653900,0x3bc93a3f,0xbb02b115,0x37b73be6,0xbb1abb46,0xb75e36aa,0xb414bb5a,0xbbbcb64e,0x394db1db,0xb9febbdd,
0xbb02bb80,0xb7b73593,0xb75ebbc9,0xbb1ab365,0x38d8b2a1,0xba5ebbd4,0x3b9135f1,0xb534bb6e,0x39963bfc,0x39baabd9,0x31db3ae9,0x3bdd3807,0xba7cad7e,0x38b03bf8,0xbbffb900,0x28b63a3f,
0xb6aa35f1,0x3b463b6e,0xb8b031db,0x3a7c3bdd,0xbb1abb91,0xb75e3534,0xba3fbbed,0xb900304e,0x3807b475,0xbae9bbaf,0x394dad7e,0xb9febbf8,0x3ab53bc9,0x385db365,0x39ba3bff,0x3996a8b6,
0x3b803b5a,0x3593b64e,0x3be63a99,0x3115b887,0xb4d53705,0x3ba03b30,0xaf0e38d8,0x3bf43a5e,0xbbbcbb02,0xb41437b7,0xbbfcba1f,0xabd93927,0x32a1b832,0xbbd4bad0,0x2248b972,0xbc00b9dc,
0x3475b6aa,0xbbafbb46,0xb4d5bad0,0xbba0b832,0x3bed3ab5,0x304eb85d,0x3b30364e,0xb705bb5a,0x2248394d,0x3c0039fe,0x38873bbc,0x3a993414,0xbbe6b927,0x31153a1f,0xb9dcaf0e,0x39723bf4,
0xbbd4bb30,0xb2a13705,0xb9bab04e,0x39963bed,0xa8b6b927,0xbbffba1f,0xbad0bbf4,0xb8322f0e,0x3baf38b0,0xb475ba7c,0x34d5b593,0xbba0bb80,0x38073b6e,0x3ae935f1,0x3bfc3a99,0x2bd9b887,
0xb04e375e,0x3bed3b1a,0x3b913baf,0x3534b475,0xbbd4b972,0x32a139dc,0x224838b0,0x3c003a7c,0xb832bb5a,0xbad0b64e,0xbb80b887,0x35933a99,0x39002bd9,0xba3fbbfc,0xb927bbbc,0xba1fb414,
0x3bfc3b02,0x2bd9b7b7,0xb04eb927,0xbbedba1f,0x35f13a7c,0x3b6e38b0,0x3ab536aa,0xb85dbb46,0xb972b1db,0x39dc3bdd,0x3ad03c00,0x3832a248,0xbba0bbbc,0xb4d53414,0xaf0e3705,0x3bf43b30,
0xa248b807,0xbc00bae9,0xba99b705,0x38873b30,0x3ad037b7,0xb832bb02,0xbb46bbf8,0xb6aa2d7e,0x3b1a3bff,0x375ea8b6,0xaf0eb8b0,0xbbf4ba7c,0x2bd9385d,0x3bfc3ab5,0x3a5e364e,0xb8d8bb5a,
0xbbf8bad0,0x2d7e3832,0x3b023bff,0x37b728b6,0xb94dbb6e,0xb9feb5f1,0x304e3887,0x3bed3a99,0x32a1b414,0xbbd4bbbc,0xb9bab534,0x39963b91,0x3b463900,0xb6aaba3f,0xbbe6bba0,0xb11534d5,
0x3115385d,0x3be63ab5,0x28b6b5f1,0xbbffbb6e,0xb900b414,0x3a3f3bbc,0x3a1f3705,0xb927bb30,0xbbfcbb1a,0x2bd9375e,0x3bed3baf,0x304eb475,0xb9babb80,0xb996b593,0x38873ad0,0x3a993832,
0x3bc93a99,0xb365b887,0xbb46b996,0x36aa39ba,0x3b023bed,0x37b7304e,0xbba0bbfc,0xb4d52bd9,0x35343927,0x3b913a1f,0xb807ba3f,0xbae9b900,0xb64ea8b6,0x3b5a3bff,0x32a1b115,0xbbd4bbe6,
0xb4d5b8b0,0xbba0ba7c,0x3a3f3b80,0x39003593,0x35342248,0xbb91bc00,0x3414385d,0x3bbc3ab5,0x3a9938d8,0xb887ba5e,0xb5f1abd9,0x3b6e3bfc,0x3bff3baf,0x28b6b475,0xbad0b927,0x38323a1f,
0xbb6eba5e,0x35f138d8,0x32a1abd9,0xbbd4bbfc,0xbbe6bbf4,0xb1152f0e,0x3972375e,0xb9dcbb1a,0xba1fbb46,0xb927b6aa,0x3baf3ad0,0xb475b832,0xb534b887,0xbb91ba99,0x3bbc3c00,0x3414a248,
0x37053900,0x3b303a3f,0xbbbcbb1a,0x3414375e,0x22483365,0x3c003bc9,0xbbddbbff,0xb1db28b6,0xb6aab2a1,0x3b463bd4,0xba7cbb5a,0xb8b0b64e,0xba1fb8d8,0x39273a5e,0xb7b7b94d,0xbb02b9fe,
0x3ae93a1f,0xb807b927,0x394d3a3f,0x39fe3900,0x3bdd3b80,0xb1dbb593,0x35f13832,0x3b6e3ad0,0x3be63c00,0x3115a248,0x28b632a1,0x3bff3bd4,0x3b023b91,0x37b73534,0xb4d5b04e,0x3ba03bed,
0xb887b94d,0xba99b9fe,0x35f13414,0xbb6ebbbc,0xb593b75e,0xbb80bb1a,0x38b037b7,0xba7cbb02,0xaf0eb365,0xbbf4bbc9,0x3a1f3972,0xb927b9dc,0x304e2248,0xbbedbc00,0x3b303ab5,0xb705b85d,
0xba3fb9dc,0x39003972,0xbbf8bbe6,0x2d7e3115,0xbae9ba99,0x38073887,0xbbfcbc00,0xabd92248,0xbb6ebb30,0x35f13705,0xbbd4bbed,0xb2a1b04e,0xbbc9bba0,0x336534d5,0xbb80bbaf,0xb593b475,
0x39723996,0x39dc39ba,0x3832385d,0x3ad03ab5,0x3927394d,0x3a1f39fe,0x37b73807,0x3b023ae9,0x38d83900,0x3a5e3a3f,0x3705375e,0x3b303b1a,0x388738b0,0x3a993a7c,0x364e36aa,0x3b5a3b46,
0x36aa3b5a,0x3b46b64e,0x38b03a99,0x3a7cb887,0xb75ebb30,0xbb1a3705,0xb900ba5e,0xba3f38d8,0x38073b02,0x3ae9b7b7,0x394d3a1f,0x39feb927,0xb85dbad0,0xbab53832,0xb996b9dc,0xb9ba3972,
0x3475bb80,0xbbafb593,0xb4d5bbc9,0xbba03365,0xb04e3bd4,0x3bed32a1,0x37053b6e,0x3b30b5f1,0xa248bbfc,0xbc00abd9,0xb887bae9,0xba993807,0x31153bf8,0x3be6ad7e,0x39723a3f,0x39dcb900,
0xbab53705,0x385d3b30,0xa2483bed,0x3c00304e,0x3972b927,0xb9dcba1f,0xb365bbf4,0xbbc92f0e,0xb7b73a7c,0x3b0238b0,0x375e3b80,0x3b1ab593,0x3414bb6e,0xbbbcb5f1,0xb94dba99,0xb9fe3887,
0x3bed34d5,0x304ebba0,0x3534bb02,0xbb91b7b7,0xbbd428b6,0x32a13bff,0x22483be6,0x3c003115,0x3ad0b5f1,0xb832bb6e,0xb593bbdd,0xbb8031db,0xb900394d,0x3a3f39fe,0x39273ae9,0x3a1fb807,
0xb94dbb02,0xb9fe37b7,0xb8d83927,0x3a5e3a1f,0x3b5a38b0,0x364eba7c,0x32a1bb46,0xbbd4b6aa,0xbbffb1db,0x28b63bdd,0x33653c00,0x3bc9a248,0x3b1ab414,0xb75ebbbc,0xb900bb30,0xba3f3705,
0x22483bbc,0x3c003414,0x3a99b534,0xb887bb91,0xb832bbaf,0xbad03475,0xb6aa3a1f,0x3b463927,0x3b1a3972,0x375eb9dc,0xaf0ebbe6,0xbbf4b115,0xbbfcb2a1,0x2bd93bd4,0x38d83b6e,0x3a5eb5f1,
0x3927b832,0xba1fbad0,0xbbafa8b6,0x34753bff,0xabd93b6e,0x3bfc35f1,0x38d8b887,0xba5eba99,0xb85dbbbc,0xbab53414,0xa2483b91,0x3c003534,0x3b803900,0x3593ba3f,0xb8b0bba0,0xba7c34d5,
0xbbe6b2a1,0x31153bd4,0x3bff364e,0x28b6bb5a,0x3900b807,0xba3fbae9,0xba1f3534,0x39273b91,0x2bd93ba0,0x3bfc34d5,0x304ebb02,0xbbedb7b7,0xb9babb46,0xb99636aa,0x38873bc9,0x3a99b365,
0x3ad03a99,0x3832b887,0xbb80b996,0xb59339ba,0xbbafb04e,0x34753bed,0x3b1aabd9,0xb75ebbfc,0x3705b927,0xbb30ba1f,0xb4143a3f,0x3bbc3900,0x35f13bff,0x3b6e28b6,0xb85dbbe6,0xbab53115,
0xb4d5bbe6,0xbba0b115,0x3a3f3b46,0x3900b6aa,0x3b9139ba,0x3534b996,0xbbbcb2a1,0x34143bd4,0xba99304e,0x38873bed,0x35f1b94d,0xbb6eb9fe,0x28b6bb02,0xbbffb7b7,0x38323bf8,0x3ad0ad7e,
0xb64e38d8,0x3b5a3a5e,0xb85dbbfc,0xbab52bd9,0xb8b0bbf4,0xba7c2f0e,0x3bff375e,0xa8b6bb1a,0x3bf836aa,0xad7ebb46,0xb7b73832,0x3b023ad0,0xb7053887,0x3b303a99,0xb807bc00,0xbae92248,
0x3b302f0e,0xb705bbf4,0x34143ba0,0x3bbc34d5,0x22483ad0,0x3c003832,0xbbddb972,0xb1db39dc,0xbb46bab5,0xb6aa385d,0x38b0b5f1,0xba7cbb6e,0x3a1fb04e,0xb927bbed,0x37b73bfc,0x3b022bd9,
0xbbbcba1f,0xb4143927,0x2bd9ba3f,0xbbfcb900,0x3887b593,0xba99bb80,0x3b5a3ad0,0x364eb832,0x38b03c00,0x3a7ca248,0xb97232a1,0x39dc3bd4,0xbbafb534,0x34753b91,0xb75ebbed,0xbb1ab04e,
0x38873bfc,0x3a992bd9,0xb5f13807,0x3b6e3ae9,0xbb80b4d5,0x35933ba0,0xba7cbbaf,0xb8b03475,0xaf0ebad0,0xbbf4b832,0x3a1fa8b6,0xb927bbff,0x3bed39ba,0x304eb996,0x37053bd4,0x3b3032a1,
0x2f0eb972,0xbbf4b9dc,0x3927b115,0xba1fbbe6,0x3bbc3a99,0x3414b887,0x394d3c00,0x39fea248,0xb64e3705,0x3b5a3b30,0xbab5b04e,0x385d3bed,0xbad0bba0,0xb83234d5,0xb6aabbaf,0xbb46b475,
0xb9dca248,0x39723c00,0xbad0b2a1,0x38323bd4,0xb927bbfc,0xba1fabd9,0xb7b7bbbc,0xbb02b414,0x3a5e2f0e,0xb8d8bbf4,0x3b3034d5,0xb705bba0,0x38873be6,0x3a993115,0x364e3b80,0x3b5a3593,
0x3bff3996,0xa8b6b9ba,0x3bc9385d,0xb365bab5,0x2d7e39fe,0x3bf8394d,0x34753ae9,0x3baf3807,0xbbedb900,0x304e3a3f,0xbb91b75e,0x35343b1a,0xb1dbba7c,0xbbddb8b0,0xb5f1bb46,0xbb6eb6aa,
0xba3fbbff,0xb90028b6,0xbbf8ba7c,0xad7e38b0,0x3807b1db,0xbae9bbdd,0xabd9b996,0xbbfcb9ba,0x3b6e3b91,0x35f1b534,0x3bd438d8,0xb2a1ba5e,0xb365375e,0x3bc93b1a,0x35933b02,0x3b8037b7,
0x31db39fe,0x3bdd394d,0x3b5a3bbc,0x364eb414,0xbb46b75e,0x36aa3b1a,0xb11537b7,0x3be63b02,0xb900bbc9,0xba3fb365,0xbbf8b9dc,0x2d7e3972,0x38d8a248,0xba5ebc00,0xb534bab5,0xbb91b85d,
0x3807ad7e,0xbae9bbf8,0xb9febbf4,0xb94daf0e,0x3bdd3b46,0x31dbb6aa,0x35f1b365,0xbb6ebbc9,0x31153996,0x3be639ba,0x3bff3ab5,0x28b6b85d,0xbb02b705,0x37b73b30,0x34d53a5e,0x3ba038d8,
0xbb91b900,0x35343a3f,0x38073b1a,0x3ae9375e,0xb996bbc9,0xb9bab365,0xb887a8b6,0x3a993bff,0x3593b2a1,0xbb80bbd4,0xbbe6bb5a,0xb115364e,0x3bf83a5e,0xad7eb8d8,0xb475b9fe,0xbbafb94d,
0x3b6e3bed,0x35f1b04e,0xb2a1b94d,0xbbd4b9fe,0x31153900,0x3be63a3f,0x39dc34d5,0xb972bba0,0xba1fb593,0x39273b80,0x3baf3bc9,0x3475b365,0xbb91bbdd,0xb53431db,0x34143996,0x3bbc39ba,
0xb75eba7c,0xbb1ab8b0,0xaf0e3593,0x3bf43b80,0x3705a248,0xbb30bc00,0xbae9b85d,0x38073ab5,0x3bdd3a5e,0xb1dbb8d8,0xbb5abbfc,0xb64e2bd9,0x39dc3baf,0x39723475,0xb365b927,0xbbc9ba1f,
0xb36531db,0x3bc93bdd,0x36aa2248,0xbb46bc00,0xbb02b8d8,0x37b73a5e,0x3ba039fe,0xb4d5b94d,0xbb91bbf8,0xb5342d7e,0x3ae93bf4,0x38072f0e,0xb64eb9dc,0xbb5ab972,0x32a138b0,0x3bd43a7c,
0x3a7c385d,0xb8b0bab5,0xb972b5f1,0x39dc3b6e,0x3bf43bbc,0x2f0eb414,0xbbf8bb30,0x2d7e3705,0x394d3b1a,0x39fe375e,0xba5ebbaf,0xb8d8b475,0xa2483593,0x3c003b80,0xb1dbb832,0xbbddbad0,
0xbbf8bbc9,0xad7e3365,0x3b023972,0xb7b7b9dc,0xb9febb5a,0xb94db64e,0x3bed3bdd,0x304eb1db,0xb2a1b807,0xbbd4bae9,0x39ba3b30,0x39963705,0x36aa2f0e,0xbb46bbf4,0x3115375e,0x3be63b1a,
0x39963ae9,0x39ba3807,0xbbddbb30,0x31db3705,0x336537b7,0x3bc93b02,0xbb80bbf8,0xb593ad7e,0xb4d5a8b6,0x3ba03bff,0xb900ba7c,0xba3fb8b0,0xb9feb85d,0x394d3ab5,0xb04eb64e,0xbbedbb5a,
0xabd9b475,0xbbfcbbaf,0x3bed3bf8,0x304ead7e,0x35f13115,0xbb6ebbe6,0x3ab53b80,0x385d3593,0x39dc3887,0xb972ba99,0x38323996,0x3ad039ba,0x3ba03ae9,0xb4d5b807,0x2f0e3534,0x3bf43b91,
0xb8d8b75e,0x3a5e3b1a,0xbb30bbaf,0xb705b475,0xbab5b9dc,0x385d3972,0xb996ba7c,0xb9bab8b0,0xbbc9bb5a,0x3365364e,0xb6aab887,0xbb46ba99,0xbbf4bbfc,0xaf0e2bd9,0xad7eb414,0xbbf8bbbc,
0x3bd43b91,0xb2a1b534,0x39ba3a5e,0x399638d8,0x3bff3bf8,0x28b6ad7e,0x38323900,0x3ad03a3f,0x3baf3be6,0x34753115,0x34d536aa,0x3ba03b46,0x3ae93b5a,0x3807364e,0x2bd931db,0x3bfc3bdd,
0xbb02bb46,0xb7b7b6aa,0xb75eb832,0xbb1abad0,0xba5ebab5,0xb8d8b85d,0xb534b64e,0xbb91bb5a,0xb996b9fe,0xb9bab94d,0xb1dbb414,0xbbddbbbc,0xb8b0b927,0xba7cba1f,0xa8b6af0e,0xbbffbbf4,
0x359335f1,0x3b803b6e,0x311531db,0x3be63bdd,0x34d53534,0x3ba03b91,0x2f0e304e,0x3bf43bed,0x34143475,0x3bbc3baf,0x2bd92d7e,0x3bfc3bf8,0x32a13365,0x3bd43bc9,0x224828b6,0x3c003bff,
0x80000,0x680060,0xc800c0,0x1280120,0xc0004,0x6c0064,0xcc00c4,0x12c0124,0x180010,0x780070,0xd800d0,0x1380130,0x1c0014,0x7c0074,0xdc00d4,0x13c0134,
0x1880180,0x1e801e0,0x2480240,0x2a802a0,0x18c0184,0x1ec01e4,0x24c0244,0x2ac02a4,0x1980190,0x1f801f0,0x2580250,0x2b802b0,0x19c0194,0x1fc01f4,0x25c0254,0x2bc02b4,
0x3080300,0x3680360,0x3c803c0,0x4280420,0x30c0304,0x36c0364,0x3cc03c4,0x42c0424,0x3180310,0x3780370,0x3d803d0,0x4380430,0x31c0314,0x37c0374,0x3dc03d4,0x43c0434,
0x4880480,0x4e804e0,0x5480540,0x5a805a0,0x48c0484,0x4ec04e4,0x54c0544,0x5ac05a4,0x4980490,0x4f804f0,0x5580550,0x5b805b0,0x49c0494,0x4fc04f4,0x55c0554,0x5bc05b4,
0x6080600,0x6680660,0x6c806c0,0x7280720,0x60c0604,0x66c0664,0x6cc06c4,0x72c0724,0x6180610,0x6780670,0x6d806d0,0x7380730,0x61c0614,0x67c0674,0x6dc06d4,0x73c0734,
0x7880780,0x7e807e0,0x8480840,0x8a808a0,0x78c0784,0x7ec07e4,0x84c0844,0x8ac08a4,0x7980790,0x7f807f0,0x8580850,0x8b808b0,0x79c0794,0x7fc07f4,0x85c0854,0x8bc08b4,
0x9080900,0x9680960,0x9c809c0,0xa280a20,0x90c0904,0x96c0964,0x9cc09c4,0xa2c0a24,0x9180910,0x9780970,0x9d809d0,0xa380a30,0x91c0914,0x97c0974,0x9dc09d4,0xa3c0a34,
0xa880a80,0xae80ae0,0xb480b40,0xba80ba0,0xa8c0a84,0xaec0ae4,0xb4c0b44,0xbac0ba4,0xa980a90,0xaf80af0,0xb580b50,0xbb80bb0,0xa9c0a94,0xafc0af4,0xb5c0b54,0xbbc0bb4,
0x280020,0x880080,0xe800e0,0x1480140,0x2c0024,0x8c0084,0xec00e4,0x14c0144,0x240020,0x840080,0xe400e0,0x1440140,0x800024,0xe00084,0x14000e4,0x1a00144,
0x1a801a0,0x2080200,0x2680260,0x2c802c0,0x1ac01a4,0x20c0204,0x26c0264,0x2cc02c4,0x1a401a0,0x2040200,0x2640260,0x2c402c0,0x20001a4,0x2600204,0x2c00264,0x32002c4,
0x3280320,0x3880380,0x3e803e0,0x4480440,0x32c0324,0x38c0384,0x3ec03e4,0x44c0444,0x3240320,0x3840380,0x3e403e0,0x4440440,0x3800324,0x3e00384,0x44003e4,0x4a00444,
0x4a804a0,0x5080500,0x5680560,0x5c805c0,0x4ac04a4,0x50c0504,0x56c0564,0x5cc05c4,0x4a404a0,0x5040500,0x5640560,0x5c405c0,0x50004a4,0x5600504,0x5c00564,0x62005c4,
0x6280620,0x6880680,0x6e806e0,0x7480740,0x62c0624,0x68c0684,0x6ec06e4,0x74c0744,0x6240620,0x6840680,0x6e406e0,0x7440740,0x6800624,0x6e00684,0x74006e4,0x7a00744,
0x7a807a0,0x8080800,0x8680860,0x8c808c0,0x7ac07a4,0x80c0804,0x86c0864,0x8cc08c4,0x7a407a0,0x8040800,0x8640860,0x8c408c0,0x80007a4,0x8600804,0x8c00864,0x92008c4,
0x9280920,0x9880980,0x9e809e0,0xa480a40,0x92c0924,0x98c0984,0x9ec09e4,0xa4c0a44,0x9240920,0x9840980,0x9e409e0,0xa440a40,0x9800924,0x9e00984,0xa4009e4,0xaa00a44,
0xaa80aa0,0xb080b00,0xb680b60,0xbc80bc0,0xaac0aa4,0xb0c0b04,0xb6c0b64,0xbcc0bc4,0xaa40aa0,0xb040b00,0xb640b60,0xbc40bc0,0xb000aa4,0xb600b04,0xbc00b64,0x300bc4,
0x300030,0x900090,0xf000f0,0x1500150,0x900034,0xf00094,0x15000f4,0x1b00154,0x340030,0x940090,0xf400f0,0x1540150,0x900034,0xf00094,0x15000f4,0x1b00154,
0x1b001b0,0x2100210,0x2700270,0x2d002d0,0x21001b4,0x2700214,0x2d00274,0x33002d4,0x1b401b0,0x2140210,0x2740270,0x2d402d0,0x21001b4,0x2700214,0x2d00274,0x33002d4,
0x3300330,0x3900390,0x3f003f0,0x4500450,0x3900334,0x3f00394,0x45003f4,0x4b00454,0x3340330,0x3940390,0x3f403f0,0x4540450,0x3900334,0x3f00394,0x45003f4,0x4b00454,
0x4b004b0,0x5100510,0x5700570,0x5d005d0,0x51004b4,0x5700514,0x5d00574,0x63005d4,0x4b404b0,0x5140510,0x5740570,0x5d405d0,0x51004b4,0x5700514,0x5d00574,0x63005d4,
0x6300630,0x6900690,0x6f006f0,0x7500750,0x6900634,0x6f00694,0x75006f4,0x7b00754,0x6340630,0x6940690,0x6f406f0,0x7540750,0x6900634,0x6f00694,0x75006f4,0x7b00754,
0x7b007b0,0x8100810,0x8700870,0x8d008d0,0x81007b4,0x8700814,0x8d00874,0x93008d4,0x7b407b0,0x8140810,0x8740870,0x8d408d0,0x81007b4,0x8700814,0x8d00874,0x93008d4,
0x9300930,0x9900990,0x9f009f0,0xa500a50,0x9900934,0x9f00994,0xa5009f4,0xab00a54,0x9340930,0x9940990,0x9f409f0,0xa540a50,0x9900934,0x9f00994,0xa5009f4,0xab00a54,
0xab00ab0,0xb100b10,0xb700b70,0xbd00bd0,0xb100ab4,0xb700b14,0xbd00b74,0x380bd4,0xab40ab0,0xb140b10,0xb740b70,0xbd40bd0,0xb100ab4,0xb700b14,0xbd00b74,0x380bd4,
0x380038,0x980098,0xf800f8,0x1580158,0x98003c,0xf8009c,0x15800fc,0x1b8015c,0x3c0038,0x9c0098,0xfc00f8,0x15c0158,0x98003c,0xf8009c,0x15800fc,0x1b8015c,
0x1b801b8,0x2180218,0x2780278,0x2d802d8,0x21801bc,0x278021c,0x2d8027c,0x33802dc,0x1bc01b8,0x21c0218,0x27c0278,0x2dc02d8,0x21801bc,0x278021c,0x2d8027c,0x33802dc,
0x3380338,0x3980398,0x3f803f8,0x4580458,0x398033c,0x3f8039c,0x45803fc,0x4b8045c,0x33c0338,0x39c0398,0x3fc03f8,0x45c0458,0x398033c,0x3f8039c,0x45803fc,0x4b8045c,
0x4b804b8,0x5180518,0x5780578,0x5d805d8,0x51804bc,0x578051c,0x5d8057c,0x63805dc,0x4bc04b8,0x51c0518,0x57c0578,0x5dc05d8,0x51804bc,0x578051c,0x5d8057c,0x63805dc,
0x6380638,0x6980698,0x6f806f8,0x7580758,0x698063c,0x6f8069c,0x75806fc,0x7b8075c,0x63c0638,0x69c0698,0x6fc06f8,0x75c0758,0x698063c,0x6f8069c,0x75806fc,0x7b8075c,
0x7b807b8,0x8180818,0x8780878,0x8d808d8,0x81807bc,0x878081c,0x8d8087c,0x93808dc,0x7bc07b8,0x81c0818,0x87c0878,0x8dc08d8,0x81807bc,0x878081c,0x8d8087c,0x93808dc,
0x9380938,0x9980998,0x9f809f8,0xa580a58,0x998093c,0x9f8099c,0xa5809fc,0xab80a5c,0x93c0938,0x99c0998,0x9fc09f8,0xa5c0a58,0x998093c,0x9f8099c,0xa5809fc,0xab80a5c,
0xab80ab8,0xb180b18,0xb780b78,0xbd80bd8,0xb180abc,0xb780b1c,0xbd80b7c,0x400bdc,0xabc0ab8,0xb1c0b18,0xb7c0b78,0xbdc0bd8,0xb180abc,0xb780b1c,0xbd80b7c,0x400bdc,
0xacc0acc,0xb2c0b2c,0xb8c0b8c,0xbec0bec,0xb2c0acc,0xb8c0b8c,0xbec0b8c,0x500050,0xacc0acc,0xb2c0b2c,0xb8c0b8c,0xbec0bec,0xb2c0b2c,0xb8c0b8c,0xbec0bec,0x500050,
0x94c094c,0x9ac09ac,0xa0c0a0c,0xa6c0a6c,0x9ac094c,0xa0c0a0c,0xa6c0a0c,0xacc0acc,0x94c094c,0x9ac09ac,0xa0c0a0c,0xa6c0a6c,0x9ac09ac,0xa0c0a0c,0xa6c0a6c,0xacc0acc,
0x7cc07cc,0x82c082c,0x88c088c,0x8ec08ec,0x82c07cc,0x88c088c,0x8ec088c,0x94c094c,0x7cc07cc,0x82c082c,0x88c088c,0x8ec08ec,0x82c082c,0x88c088c,0x8ec08ec,0x94c094c,
0x64c064c,0x6ac06ac,0x70c070c,0x76c076c,0x6ac064c,0x70c070c,0x76c070c,0x7cc07cc,0x64c064c,0x6ac06ac,0x70c070c,0x76c076c,0x6ac06ac,0x70c070c,0x76c076c,0x7cc07cc,
0x4cc04cc,0x52c052c,0x58c058c,0x5ec05ec,0x52c04cc,0x58c058c,0x5ec058c,0x64c064c,0x4cc04cc,0x52c052c,0x58c058c,0x5ec05ec,0x52c052c,0x58c058c,0x5ec05ec,0x64c064c,
0x34c034c,0x3ac03ac,0x40c040c,0x46c046c,0x3ac034c,0x40c040c,0x46c040c,0x4cc04cc,0x34c034c,0x3ac03ac,0x40c040c,0x46c046c,0x3ac03ac,0x40c040c,0x46c046c,0x4cc04cc,
0x1cc01cc,0x22c022c,0x28c028c,0x2ec02ec,0x22c01cc,0x28c028c,0x2ec028c,0x34c034c,0x1cc01cc,0x22c022c,0x28c028c,0x2ec02ec,0x22c022c,0x28c028c,0x2ec02ec,0x34c034c,
0x4c004c,0xac00ac,0x10c010c,0x16c016c,0xac004c,0x10c010c,0x16c010c,0x1cc01cc,0x4c004c,0xac00ac,0x10c010c,0x16c016c,0xac00ac,0x10c010c,0x16c016c,0x1cc01cc,
0xac80ac8,0xb280b28,0xb880b88,0xbe80be8,0xb280ac8,0xb880b88,0xbe80b88,0x4c004c,0xac80ac8,0xb280b28,0xb880b88,0xbe80be8,0xb280b28,0xb880b88,0xbe80be8,0x4c004c,
0x9480948,0x9a809a8,0xa080a08,0xa680a68,0x9a80948,0xa080a08,0xa680a08,0xac80ac8,0x9480948,0x9a809a8,0xa080a08,0xa680a68,0x9a809a8,0xa080a08,0xa680a68,0xac80ac8,
0x7c807c8,0x8280828,0x8880888,0x8e808e8,0x82807c8,0x8880888,0x8e80888,0x9480948,0x7c807c8,0x8280828,0x8880888,0x8e808e8,0x8280828,0x8880888,0x8e808e8,0x9480948,
0x6480648,0x6a806a8,0x7080708,0x7680768,0x6a80648,0x7080708,0x7680708,0x7c807c8,0x6480648,0x6a806a8,0x7080708,0x7680768,0x6a806a8,0x7080708,0x7680768,0x7c807c8,
0x4c804c8,0x5280528,0x5880588,0x5e805e8,0x52804c8,0x5880588,0x5e80588,0x6480648,0x4c804c8,0x5280528,0x5880588,0x5e805e8,0x5280528,0x5880588,0x5e805e8,0x6480648,
0x3480348,0x3a803a8,0x4080408,0x4680468,0x3a80348,0x4080408,0x4680408,0x4c804c8,0x3480348,0x3a803a8,0x4080408,0x4680468,0x3a803a8,0x4080408,0x4680468,0x4c804c8,
0x1c801c8,0x2280228,0x2880288,0x2e802e8,0x22801c8,0x2880288,0x2e80288,0x3480348,0x1c801c8,0x2280228,0x2880288,0x2e802e8,0x2280228,0x2880288,0x2e802e8,0x3480348,
0x480048,0xa800a8,0x1080108,0x1680168,0xa80048,0x1080108,0x1680108,0x1c801c8,0x480048,0xa800a8,0x1080108,0x1680168,0xa800a8,0x1080108,0x1680168,0x1c801c8,
0xac40ac4,0xb240b24,0xb840b84,0xbe40be4,0xb240ac4,0xb840b84,0xbe40b84,0x480048,0xac40ac4,0xb240b24,0xb840b84,0xbe40be4,0xb240b24,0xb840b84,0xbe40be4,0x480048,
0x9440944,0x9a409a4,0xa040a04,0xa640a64,0x9a40944,0xa040a04,0xa640a04,0xac40ac4,0x9440944,0x9a409a4,0xa040a04,0xa640a64,0x9a409a4,0xa040a04,0xa640a64,0xac40ac4,
0x7c407c4,0x8240824,0x8840884,0x8e408e4,0x82407c4,0x8840884,0x8e40884,0x9440944,0x7c407c4,0x8240824,0x8840884,0x8e408e4,0x8240824,0x8840884,0x8e408e4,0x9440944,
0x6440644,0x6a406a4,0x7040704,0x7640764,0x6a40644,0x7040704,0x7640704,0x7c407c4,0x6440644,0x6a406a4,0x7040704,0x7640764,0x6a406a4,0x7040704,0x7640764,0x7c407c4,
0x4c404c4,0x5240524,0x5840584,0x5e405e4,0x52404c4,0x5840584,0x5e40584,0x6440644,0x4c404c4,0x5240524,0x5840584,0x5e405e4,0x5240524,0x5840584,0x5e405e4,0x6440644,
0x3440344,0x3a403a4,0x4040404,0x4640464,0x3a40344,0x4040404,0x4640404,0x4c404c4,0x3440344,0x3a403a4,0x4040404,0x4640464,0x3a403a4,0x4040404,0x4640464,0x4c404c4,
0x1c401c4,0x2240224,0x2840284,0x2e402e4,0x22401c4,0x2840284,0x2e40284,0x3440344,0x1c401c4,0x2240224,0x2840284,0x2e402e4,0x2240224,0x2840284,0x2e402e4,0x3440344,
0x440044,0xa400a4,0x1040104,0x1640164,0xa40044,0x1040104,0x1640104,0x1c401c4,0x440044,0xa400a4,0x1040104,0x1640164,0xa400a4,0x1040104,0x1640164,0x1c401c4,
0xac00ac0,0xb200b20,0xb800b80,0xbe00be0,0xb200ac0,0xb800b80,0xbe00b80,0x440044,0xac00ac0,0xb200b20,0xb800b80,0xbe00be0,0xb200b20,0xb800b80,0xbe00be0,0x440044,
0x9400940,0x9a009a0,0xa000a00,0xa600a60,0x9a00940,0xa000a00,0xa600a00,0xac00ac0,0x9400940,0x9a009a0,0xa000a00,0xa600a60,0x9a009a0,0xa000a00,0xa600a60,0xac00ac0,
0x7c007c0,0x8200820,0x8800880,0x8e008e0,0x82007c0,0x8800880,0x8e00880,0x9400940,0x7c007c0,0x8200820,0x8800880,0x8e008e0,0x8200820,0x8800880,0x8e008e0,0x9400940,
0x6400640,0x6a006a0,0x7000700,0x7600760,0x6a00640,0x7000700,0x7600700,0x7c007c0,0x6400640,0x6a006a0,0x7000700,0x7600760,0x6a006a0,0x7000700,0x7600760,0x7c007c0,
0x4c004c0,0x5200520,0x5800580,0x5e005e0,0x52004c0,0x5800580,0x5e00580,0x6400640,0x4c004c0,0x5200520,0x5800580,0x5e005e0,0x5200520,0x5800580,0x5e005e0,0x6400640,
0x3400340,0x3a003a0,0x4000400,0x4600460,0x3a00340,0x4000400,0x4600400,0x4c004c0,0x3400340,0x3a003a0,0x4000400,0x4600460,0x3a003a0,0x4000400,0x4600460,0x4c004c0,
0x1c001c0,0x2200220,0x2800280,0x2e002e0,0x22001c0,0x2800280,0x2e00280,0x3400340,0x1c001c0,0x2200220,0x2800280,0x2e002e0,0x2200220,0x2800280,0x2e002e0,0x3400340,
0x400040,0xa000a0,0x1000100,0x1600160,0xa00040,0x1000100,0x1600100,0x1c001c0,0x400040,0xa000a0,0x1000100,0x1600160,0xa000a0,0x1000100,0x1600160,0x1c001c0,
0x30003000,0x30003000,0x30003000,0x30003000,0x30003000,0x30003000,0x30003000,0x30003000,0x0,0x0,0x0,0x0,0x0,0x0,0x0,0x0,
0x30003000,0x30003000,0x30003000,0x30003000,0x30003000,0x30003000,0x30003000,0x30003000,0x0,0x0,0x0,0x0,0x0,0x0,0x0,0x0,
0x2a1f2da8,0xaf64ada8,0xaa1fada8,0x2f642da8,0x2f643000,0xaa1f0000,0xaf64b000,0x2a1f8000,0x2f642da8,0x2a1f2da8,0xaf64ada8,0xaa1fada8,0x2a1f0000,0x2f643000,0xaa1f0000,0xaf64b000,
0x263e2c72,0xafd9aea7,0xa63eac72,0x2fd92ea7,0x2ea72fd9,0xac72a63e,0xaea7afd9,0x2c72263e,0x2fd92ea7,0x263e2c72,0xafd9aea7,0xa63eac72,0x2c72263e,0x2ea72fd9,0xac72a63e,0xaea7afd9,
0x2da80000,0xada80000,0x2da88000,0xada80000,0x2da83000,0xada8b000,0x2da83000,0xada8b000,0x2da83000,0xada8b000,0x2da83000,0xada8b000,0xada80000,0x2da88000,0xada80000,0x2da88000,
0x2f642a1f,0xaf64aa1f,0x2f642a1f,0xaf64aa1f,0x2a1f2f64,0xaa1faf64,0x2a1f2f64,0xaa1faf64,0x2a1f2f64,0xaa1faf64,0x2a1f2f64,0xaa1faf64,0xaf64aa1f,0x2f642a1f,0xaf64aa1f,0x2f642a1f,
0xaa1f2da8,0x2f642da8,0x2a1fada8,0xaf64ada8,0x2f640000,0xaa1fb000,0xaf640000,0x2a1f3000,0xaf64ada8,0xaa1f2da8,0x2f642da8,0x2a1fada8,0x2a1f3000,0x2f648000,0xaa1fb000,0xaf640000,
0xaea7263e,0x2c722fd9,0x2ea7a63e,0xac72afd9,0x2fd92c72,0x263eaea7,0xafd9ac72,0xa63e2ea7,0xac72afd9,0xaea7263e,0x2c722fd9,0x2ea7a63e,0xa63e2ea7,0x2fd92c72,0x263eaea7,0xafd9ac72,
0xada82da8,0xada82da8,0xada82da8,0xada82da8,0x2da8ada8,0x2da8ada8,0x2da8ada8,0x2da8ada8,0x2da82da8,0x2da82da8,0x2da82da8,0x2da82da8,0xada8ada8,0xada8ada8,0xada8ada8,0xada8ada8,
0x3000,0x3000,0x3000,0x80003000,0x8000b000,0x8000b000,0x8000b000,0x8000b000,0x30000000,0x30008000,0x30008000,0x30008000,0xb0000000,0xb0000000,0xb0000000,0xb0000000,
0x2ea7263e,0xac722fd9,0xaea7a63e,0x2c72afd9,0xafd92c72,0xa63eaea7,0x2fd9ac72,0x263e2ea7,0x2c72afd9,0x2ea7263e,0xac722fd9,0xaea7a63e,0x263e2ea7,0xafd92c72,0xa63eaea7,0x2fd9ac72,
0x2f64ada8,0x2a1f2da8,0xaf642da8,0xaa1fada8,0xaa1f3000,0xaf640000,0x2a1fb000,0x2f648000,0xaa1fada8,0x2f64ada8,0x2a1f2da8,0xaf642da8,0x2f640000,0xaa1f3000,0xaf640000,0x2a1fb000,
0xaa1f2f64,0x2a1faf64,0xaa1f2f64,0x2a1faf64,0x2f64aa1f,0xaf642a1f,0x2f64aa1f,0xaf642a1f,0xaf642a1f,0x2f64aa1f,0xaf642a1f,0x2f64aa1f,0xaa1f2f64,0x2a1faf64,0xaa1f2f64,0x2a1faf64,
0x2da80000,0xada80000,0x2da88000,0xada80000,0x2da8b000,0xada83000,0x2da8b000,0xada83000,0xada83000,0x2da8b000,0xada83000,0x2da8b000,0x2da88000,0xada80000,0x2da88000,0xada88000,
0xa63e2c72,0x2fd9aea7,0x263eac72,0xafd92ea7,0xaea72fd9,0x2c72a63e,0x2ea7afd9,0xac72263e,0xafd92ea7,0xa63e2c72,0x2fd9aea7,0x263eac72,0xac72263e,0xaea72fd9,0x2c72a63e,0x2ea7afd9,
0x2f64ada8,0x2a1fada8,0xaf642da8,0xaa1f2da8,0x2a1f0000,0x2f64b000,0xaa1f0000,0xaf643000,0xaa1f2da8,0x2f64ada8,0x2a1fada8,0xaf642da8,0xaf643000,0x2a1f8000,0x2f64b000,0xaa1f8000,
0xb0003000,0xb0003000,0xb0003000,0xb0003000,0xb0003000,0xb0003000,0xb0003000,0xb0003000,0x0,0x8000,0x8000,0x80008000,0x8000,0x8000,0x8000,0x8000,
0x80000000,0x80000000,0x80008000,0x80008000,0x80000000,0x80008000,0x80008000,0x80008000,0xb0003000,0xb0003000,0xb0003000,0xb0003000,0xb0003000,0xb0003000,0xb0003000,0xb0003000,
0xaa1f2da8,0x2f64ada8,0x2a1fada8,0xaf642da8,0xaf643000,0x2a1f0000,0x2f64b000,0xaa1f8000,0xaf642da8,0xaa1f2da8,0x2f64ada8,0x2a1fada8,0xaa1f0000,0xaf643000,0x2a1f0000,0x2f64b000,
0x2fd9aea7,0x263eac72,0xafd92ea7,0xa63e2c72,0x2c72a63e,0x2ea7afd9,0xac72263e,0xaea72fd9,0xa63e2c72,0x2fd9aea7,0x263eac72,0xafd92ea7,0xaea72fd9,0x2c72a63e,0x2ea7afd9,0xac72263e,
0xada80000,0x2da80000,0xada88000,0x2da80000,0xada83000,0x2da8b000,0xada83000,0x2da8b000,0xada83000,0x2da8b000,0xada83000,0x2da8b000,0x2da80000,0xada88000,0x2da88000,0xada88000,
0xaa1f2f64,0x2a1faf64,0xaa1f2f64,0x2a1faf64,0x2f64aa1f,0xaf642a1f,0x2f64aa1f,0xaf642a1f,0x2f64aa1f,0xaf642a1f,0x2f64aa1f,0xaf642a1f,0x2a1faf64,0xaa1f2f64,0x2a1faf64,0xaa1f2f64,
0x2a1f2da8,0xaf642da8,0xaa1fada8,0x2f64ada8,0xaf640000,0x2a1fb000,0x2f640000,0xaa1f3000,0x2f64ada8,0x2a1f2da8,0xaf642da8,0xaa1fada8,0xaa1f3000,0xaf648000,0x2a1fb000,0x2f640000,
0x2c72afd9,0x2ea7263e,0xac722fd9,0xaea7a63e,0x263e2ea7,0xafd92c72,0xa63eaea7,0x2fd9ac72,0xaea7a63e,0x2c72afd9,0x2ea7263e,0xac722fd9,0x2fd9ac72,0x263e2ea7,0xafd92c72,0xa63eaea7,
0x2da8ada8,0x2da8ada8,0x2da8ada8,0x2da8ada8,0xada82da8,0xada82da8,0xada82da8,0xada82da8,0x2da82da8,0x2da82da8,0x2da82da8,0x2da82da8,0xada8ada8,0xada8ada8,0xada8ada8,0xada8ada8,
0x80003000,0x80003000,0x80003000,0x3000,0xb000,0x8000b000,0xb000,0xb000,0xb0000000,0xb0008000,0xb0008000,0xb0008000,0x30000000,0x30000000,0x30000000,0x30008000,
0x2c722fd9,0x2ea7a63e,0xac72afd9,0xaea7263e,0x263eaea7,0xafd9ac72,0xa63e2ea7,0x2fd92c72,0xaea7263e,0x2c722fd9,0x2ea7a63e,0xac72afd9,0x2fd92c72,0x263eaea7,0xafd9ac72,0xa63e2ea7,
0xaf64ada8,0xaa1f2da8,0x2f642da8,0x2a1fada8,0x2a1f3000,0x2f648000,0xaa1fb000,0xaf648000,0x2a1fada8,0xaf64ada8,0xaa1f2da8,0x2f642da8,0xaf640000,0x2a1f3000,0x2f648000,0xaa1fb000,
0x2f642a1f,0xaf64aa1f,0x2f642a1f,0xaf64aa1f,0x2a1f2f64,0xaa1faf64,0x2a1f2f64,0xaa1faf64,0xaa1faf64,0x2a1f2f64,0xaa1faf64,0x2a1f2f64,0x2f642a1f,0xaf64aa1f,0x2f642a1f,0xaf64aa1f,
0xada80000,0x2da80000,0xada88000,0x2da88000,0xada8b000,0x2da83000,0xada8b000,0x2da83000,0x2da83000,0xada8b000,0x2da83000,0xada8b000,0xada88000,0x2da88000,0xada88000,0x2da80000,
0x2fd92ea7,0x263e2c72,0xafd9aea7,0xa63eac72,0x2c72263e,0x2ea72fd9,0xac72a63e,0xaea7afd9,0xa63eac72,0x2fd92ea7,0x263e2c72,0xafd9aea7,0xaea7afd9,0x2c72263e,0x2ea72fd9,0xac72a63e,
0xaf64ada8,0xaa1fada8,0x2f642da8,0x2a1f2da8,0xaa1f0000,0xaf64b000,0x2a1f0000,0x2f643000,0x2a1f2da8,0xaf64ada8,0xaa1fada8,0x2f642da8,0x2f643000,0xaa1f8000,0xaf64b000,0x2a1f0000,
0x80008000,0x80008000,0x80008000,0x80008000,0x80008000,0x80008000,0x80008000,0x80008000,0x30003000,0x30003000,0x30003000,0x30003000,0x30003000,0x30003000,0x30003000,0x30003000,
0x80008000,0x80008000,0x80008000,0x80008000,0x80008000,0x80008000,0x80008000,0x80008000,0x30003000,0x30003000,0x30003000,0x30003000,0x30003000,0x30003000,0x30003000,0x30003000,
0xaf64ada8,0xaa1fada8,0x2f642da8,0x2a1f2da8,0xaa1f8000,0xaf64b000,0x2a1f8000,0x2f643000,0x2a1f2da8,0xaf64ada8,0xaa1fada8,0x2f642da8,0x2f643000,0xaa1f0000,0xaf64b000,0x2a1f8000,
0xafd9aea7,0xa63eac72,0x2fd92ea7,0x263e2c72,0xac72a63e,0xaea7afd9,0x2c72263e,0x2ea72fd9,0x263e2c72,0xafd9aea7,0xa63eac72,0x2fd92ea7,0x2ea72fd9,0xac72a63e,0xaea7afd9,0x2c72263e,
0x2da83000,0xada8b000,0x2da83000,0xada8b000,0xada80000,0x2da88000,0xada80000,0x2da88000,0xada88000,0x2da88000,0xada80000,0x2da88000,0xada8b000,0x2da83000,0xada8b000,0x2da83000,
0x2a1f2f64,0xaa1faf64,0x2a1f2f64,0xaa1faf64,0xaf64aa1f,0x2f642a1f,0xaf64aa1f,0x2f642a1f,0xaf64aa1f,0x2f642a1f,0xaf64aa1f,0x2f642a1f,0xaa1faf64,0x2a1f2f64,0xaa1faf64,0x2a1f2f64,
0xaf64ada8,0xaa1f2da8,0x2f642da8,0x2a1fada8,0x2a1f3000,0x2f648000,0xaa1fb000,0xaf640000,0x2a1fada8,0xaf64ada8,0xaa1f2da8,0x2f642da8,0xaf648000,0x2a1f3000,0x2f648000,0xaa1fb000,
0xac72afd9,0xaea7263e,0x2c722fd9,0x2ea7a63e,0xa63e2ea7,0x2fd92c72,0x263eaea7,0xafd9ac72,0x2ea7a63e,0xac72afd9,0xaea7263e,0x2c722fd9,0xafd9ac72,0xa63e2ea7,0x2fd92c72,0x263eaea7,
0xada8ada8,0xada8ada8,0xada8ada8,0xada8ada8,0x2da82da8,0x2da82da8,0x2da82da8,0x2da82da8,0xada82da8,0xada82da8,0xada82da8,0xada82da8,0x2da8ada8,0x2da8ada8,0x2da8ada8,0x2da8ada8,
0xb0008000,0xb0000000,0xb0000000,0xb0000000,0x30008000,0x30008000,0x30008000,0x30008000,0x3000,0x3000,0x3000,0x80003000,0x8000b000,0x8000b000,0x8000b000,0x8000b000,
0xac722fd9,0xaea7a63e,0x2c72afd9,0x2ea7263e,0xa63eaea7,0x2fd9ac72,0x263e2ea7,0xafd92c72,0x2ea7263e,0xac722fd9,0xaea7a63e,0x2c72afd9,0xafd92c72,0xa63eaea7,0x2fd9ac72,0x263e2ea7,
0x2a1f2da8,0xaf642da8,0xaa1fada8,0x2f64ada8,0xaf648000,0x2a1fb000,0x2f648000,0xaa1f3000,0x2f64ada8,0x2a1f2da8,0xaf642da8,0xaa1fada8,0xaa1f3000,0xaf640000,0x2a1fb000,0x2f648000,
0xaf642a1f,0x2f64aa1f,0xaf642a1f,0x2f64aa1f,0xaa1f2f64,0x2a1faf64,0xaa1f2f64,0x2a1faf64,0x2a1faf64,0xaa1f2f64,0x2a1faf64,0xaa1f2f64,0xaf642a1f,0x2f64aa1f,0xaf642a1f,0x2f64aa1f,
0xada83000,0x2da8b000,0xada83000,0x2da8b000,0x2da88000,0xada80000,0x2da88000,0xada88000,0xada88000,0x2da88000,0xada80000,0x2da88000,0xada83000,0x2da8b000,0xada83000,0x2da8b000,
0xafd92ea7,0xa63e2c72,0x2fd9aea7,0x263eac72,0xac72263e,0xaea72fd9,0x2c72a63e,0x2ea7afd9,0x263eac72,0xafd92ea7,0xa63e2c72,0x2fd9aea7,0x2ea7afd9,0xac72263e,0xaea72fd9,0x2c72a63e,
0xaa1f2da8,0x2f64ada8,0x2a1fada8,0xaf642da8,0xaf643000,0x2a1f8000,0x2f64b000,0xaa1f8000,0xaf642da8,0xaa1f2da8,0x2f64ada8,0x2a1fada8,0xaa1f8000,0xaf643000,0x2a1f8000,0x2f64b000,
0x80008000,0x80000000,0x80000000,0x0,0x80000000,0x80000000,0x80000000,0x80000000,0xb0003000,0xb0003000,0xb0003000,0xb0003000,0xb0003000,0xb0003000,0xb0003000,0xb0003000,
0x3000b000,0x3000b000,0x3000b000,0x3000b000,0x3000b000,0x3000b000,0x3000b000,0x3000b000,0x80000000,0x80000000,0x80008000,0x80008000,0x80000000,0x80008000,0x80008000,0x80008000,
0x2f64ada8,0x2a1fada8,0xaf642da8,0xaa1f2da8,0x2a1f8000,0x2f64b000,0xaa1f8000,0xaf643000,0xaa1f2da8,0x2f64ada8,0x2a1fada8,0xaf642da8,0xaf643000,0x2a1f0000,0x2f64b000,0xaa1f8000,
0x263eac72,0xafd92ea7,0xa63e2c72,0x2fd9aea7,0x2ea7afd9,0xac72263e,0xaea72fd9,0x2c72a63e,0x2fd9aea7,0x263eac72,0xafd92ea7,0xa63e2c72,0x2c72a63e,0x2ea7afd9,0xac72263e,0xaea72fd9,
0xada83000,0x2da8b000,0xada83000,0x2da8b000,0x2da80000,0xada88000,0x2da88000,0xada88000,0x2da88000,0xada88000,0x2da80000,0xada88000,0x2da8b000,0xada83000,0x2da8b000,0xada83000,
0x2f64aa1f,0xaf642a1f,0x2f64aa1f,0xaf642a1f,0x2a1faf64,0xaa1f2f64,0x2a1faf64,0xaa1f2f64,0x2a1faf64,0xaa1f2f64,0x2a1faf64,0xaa1f2f64,0xaf642a1f,0x2f64aa1f,0xaf642a1f,0x2f64aa1f,
0x2f64ada8,0x2a1f2da8,0xaf642da8,0xaa1fada8,0xaa1f3000,0xaf648000,0x2a1fb000,0x2f640000,0xaa1fada8,0x2f64ada8,0x2a1f2da8,0xaf642da8,0x2f648000,0xaa1f3000,0xaf648000,0x2a1fb000,
0xaea7a63e,0x2c72afd9,0x2ea7263e,0xac722fd9,0x2fd9ac72,0x263e2ea7,0xafd92c72,0xa63eaea7,0xac722fd9,0xaea7a63e,0x2c72afd9,0x2ea7263e,0xa63eaea7,0x2fd9ac72,0x263e2ea7,0xafd92c72,
0xada8ada8,0xada8ada8,0xada8ada8,0xada8ada8,0x2da82da8,0x2da82da8,0x2da82da8,0x2da82da8,0x2da8ada8,0x2da8ada8,0x2da8ada8,0x2da8ada8,0xada82da8,0xada82da8,0xada82da8,0xada82da8,
0x30008000,0x30000000,0x30000000,0x30000000,0xb0008000,0xb0008000,0xb0008000,0xb0000000,0x80003000,0x80003000,0x80003000,0x3000,0xb000,0x8000b000,0xb000,0xb000,
0x2ea7a63e,0xac72afd9,0xaea7263e,0x2c722fd9,0xafd9ac72,0xa63e2ea7,0x2fd92c72,0x263eaea7,0x2c722fd9,0x2ea7a63e,0xac72afd9,0xaea7263e,0x263eaea7,0xafd9ac72,0xa63e2ea7,0x2fd92c72,
0xaa1f2da8,0x2f642da8,0x2a1fada8,0xaf64ada8,0x2f648000,0xaa1fb000,0xaf640000,0x2a1f3000,0xaf64ada8,0xaa1f2da8,0x2f642da8,0x2a1fada8,0x2a1f3000,0x2f648000,0xaa1fb000,0xaf648000,
0xaa1faf64,0x2a1f2f64,0xaa1faf64,0x2a1f2f64,0x2f642a1f,0xaf64aa1f,0x2f642a1f,0xaf64aa1f,0xaf64aa1f,0x2f642a1f,0xaf64aa1f,0x2f642a1f,0xaa1faf64,0x2a1f2f64,0xaa1faf64,0x2a1f2f64,
0x2da83000,0xada8b000,0x2da83000,0xada8b000,0xada88000,0x2da88000,0xada88000,0x2da80000,0x2da88000,0xada88000,0x2da80000,0xada80000,0x2da83000,0xada8b000,0x2da83000,0xada8b000,
0xa63eac72,0x2fd92ea7,0x263e2c72,0xafd9aea7,0xaea7afd9,0x2c72263e,0x2ea72fd9,0xac72a63e,0xafd9aea7,0xa63eac72,0x2fd92ea7,0x263e2c72,0xac72a63e,0xaea7afd9,0x2c72263e,0x2ea72fd9,
0x2a1f2da8,0xaf64ada8,0xaa1fada8,0x2f642da8,0x2f643000,0xaa1f8000,0xaf64b000,0x2a1f0000,0x2f642da8,0x2a1f2da8,0xaf64ada8,0xaa1fada8,0x2a1f8000,0x2f643000,0xaa1f8000,0xaf64b000,
0x3c003c00,0x3c003c00,0x3c003c00,0x3c003c00,0x3c003c00,0x3c003c00,0x3c003c00,0x3c003c00,0x80008000,0x80008000,0x80008000,0x80008000,0x80008000,0x80008000,0x80008000,0x80008000,
0x3bd93c00,0x3aa73b64,0x387239a8,0x323e361f,0xb23e0000,0xb872b61f,0xbaa7b9a8,0xbbd9bb64,0xb23e8000,0xb872b61f,0xbaa7b9a8,0xbbd9bb64,0xbbd9bc00,0xbaa7bb64,0xb872b9a8,0xb23eb61f,
0xbb64bc00,0xb61fb9a8,0x361f8000,0x3b6439a8,0x3b643c00,0x361f39a8,0xb61f0000,0xbb64b9a8,0x361f8000,0x3b6439a8,0x3b643c00,0x361f39a8,0xb61f8000,0xbb64b9a8,0xbb64bc00,0xb61fb9a8,
0x38728000,0x3bd93b64,0x323e39a8,0xbaa7b61f,0x3aa73c00,0xb23e361f,0xbbd9b9a8,0xb872bb64,0x3aa73c00,0xb23e361f,0xbbd9b9a8,0xb872bb64,0xb8728000,0xbbd9bb64,0xb23eb9a8,0x3aa7361f,
0xbc008000,0x3c008000,0xbc000000,0x3c008000,0xbc000000,0x3c008000,0xbc000000,0x3c008000,0x3c00,0x8000bc00,0x3c00,0x8000bc00,0x3c00,0x8000bc00,0x80003c00,0x8000bc00,
0xbbd98000,0x3aa7361f,0xb872b9a8,0x323e3b64,0x323ebc00,0xb8723b64,0x3aa7b9a8,0xbbd9361f,0xb23e3c00,0x3872bb64,0xbaa739a8,0x3bd9b61f,0xbbd90000,0x3aa7361f,0xb872b9a8,0x323e3b64,
0x3b648000,0xb61fb9a8,0xb61f3c00,0x3b64b9a8,0xbb648000,0x361f39a8,0x361fbc00,0xbb6439a8,0x361fbc00,0xbb6439a8,0x3b648000,0xb61fb9a8,0xb61f3c00,0x3b64b9a8,0xbb640000,0x361f39a8,
0xb8723c00,0x3bd9b61f,0xb23eb9a8,0xbaa73b64,0xbaa78000,0xb23e3b64,0x3bd9b9a8,0xb872b61f,0x3aa78000,0x323ebb64,0xbbd939a8,0x3872361f,0xb8723c00,0x3bd9b61f,0xb23eb9a8,0xbaa73b64,
0xbbd93c00,0xbaa73b64,0xb87239a8,0xb23e361f,0x323e8000,0x3872b61f,0x3aa7b9a8,0x3bd9bb64,0x323e8000,0x3872b61f,0x3aa7b9a8,0x3bd9bb64,0x3bd9bc00,0x3aa7bb64,0x3872b9a8,0x323eb61f,
0xbc003c00,0xbc003c00,0xbc003c00,0xbc003c00,0xbc003c00,0xbc003c00,0xbc003c00,0xbc003c00,0x80008000,0x80000000,0x80000000,0x80000000,0x80000000,0x80000000,0x0,0x80000000,
0xb8728000,0xbbd93b64,0xb23e39a8,0x3aa7b61f,0xbaa73c00,0x323e361f,0x3bd9b9a8,0x3872bb64,0xbaa73c00,0x323e361f,0x3bd9b9a8,0x3872bb64,0x38728000,0x3bd9bb64,0x323eb9a8,0xbaa7361f,
0x3b64bc00,0x361fb9a8,0xb61f8000,0xbb6439a8,0xbb643c00,0xb61f39a8,0x361f0000,0x3b64b9a8,0xb61f8000,0xbb6439a8,0xbb643c00,0xb61f39a8,0x361f8000,0x3b64b9a8,0x3b64bc00,0x361fb9a8,
0x3bd98000,0xbaa7361f,0x3872b9a8,0xb23e3b64,0xb23ebc00,0x38723b64,0xbaa7b9a8,0x3bd9361f,0x323e3c00,0xb872bb64,0x3aa739a8,0xbbd9b61f,0x3bd98000,0xbaa7361f,0x3872b9a8,0xb23e3b64,
0x3c008000,0xbc008000,0x3c000000,0xbc008000,0x3c000000,0xbc008000,0x3c000000,0xbc000000,0x80003c00,0xbc00,0x80003c00,0x8000bc00,0x80003c00,0xbc00,0x80003c00,0xbc00,
0x38723c00,0xbbd9b61f,0x323eb9a8,0x3aa73b64,0x3aa78000,0x323e3b64,0xbbd9b9a8,0x3872b61f,0xbaa78000,0xb23ebb64,0x3bd939a8,0xb872361f,0x38723c00,0xbbd9b61f,0x323eb9a8,0x3aa73b64,
0xbb640000,0x361fb9a8,0x361f3c00,0xbb64b9a8,0x3b648000,0xb61f39a8,0xb61fbc00,0x3b6439a8,0xb61fbc00,0x3b6439a8,0xbb640000,0x361fb9a8,0x361f3c00,0xbb64b9a8,0x3b648000,0xb61f39a8,
0x39a83c00,0xb9a80000,0xb9a8bc00,0x39a88000,0x39a83c00,0xb9a80000,0xb9a8bc00,0x39a88000,0xb9a88000,0xb9a8bc00,0x39a88000,0x39a83c00,0xb9a80000,0xb9a8bc00,0x39a88000,0x39a83c00,
0x38723c00,0xbbd9b61f,0x323eb9a8,0x3aa73b64,0xbaa70000,0xb23ebb64,0x3bd939a8,0xb872361f,0xbaa78000,0xb23ebb64,0x3bd939a8,0xb872361f,0xb872bc00,0x3bd9361f,0xb23e39a8,0xbaa7bb64,
0xb61fbc00,0x3b6439a8,0xbb640000,0x361fb9a8,0x361f3c00,0xbb64b9a8,0x3b648000,0xb61f39a8,0x3b648000,0xb61f39a8,0xb61fbc00,0x3b6439a8,0xbb648000,0x361fb9a8,0x361f3c00,0xbb64b9a8,
0x3bd98000,0xbaa7361f,0x3872b9a8,0xb23e3b64,0x323e3c00,0xb872bb64,0x3aa739a8,0xbbd9b61f,0x323e3c00,0xb872bb64,0x3aa739a8,0xbbd9b61f,0xbbd98000,0x3aa7b61f,0xb87239a8,0x323ebb64,
0xb9a88000,0xb9a83c00,0x39a88000,0x39a8bc00,0xb9a80000,0xb9a83c00,0x39a88000,0x39a8bc00,0xb9a83c00,0x39a88000,0x39a8bc00,0xb9a80000,0xb9a83c00,0x39a88000,0x39a8bc00,0xb9a88000,
0xb8728000,0xbbd93b64,0xb23e39a8,0x3aa7b61f,0x3aa7bc00,0xb23eb61f,0xbbd939a8,0xb8723b64,0xbaa73c00,0x323e361f,0x3bd9b9a8,0x3872bb64,0xb8728000,0xbbd93b64,0xb23e39a8,0x3aa7b61f,
0x361f8000,0x3b64b9a8,0x3b64bc00,0x361fb9a8,0xb61f8000,0xbb6439a8,0xbb643c00,0xb61f39a8,0x3b64bc00,0x361fb9a8,0xb61f8000,0xbb6439a8,0xbb643c00,0xb61f39a8,0x361f8000,0x3b64b9a8,
0xbbd93c00,0xbaa73b64,0xb87239a8,0xb23e361f,0xb23e8000,0xb872361f,0xbaa739a8,0xbbd93b64,0x323e8000,0x3872b61f,0x3aa7b9a8,0x3bd9bb64,0xbbd93c00,0xbaa73b64,0xb87239a8,0xb23e361f,
0xb8723c00,0x3bd9b61f,0xb23eb9a8,0xbaa73b64,0x3aa78000,0x323ebb64,0xbbd939a8,0x3872361f,0x3aa78000,0x323ebb64,0xbbd939a8,0x3872361f,0x3872bc00,0xbbd9361f,0x323e39a8,0x3aa7bb64,
0xb9a83c00,0x39a80000,0x39a8bc00,0xb9a88000,0xb9a83c00,0x39a88000,0x39a8bc00,0xb9a88000,0x39a88000,0x39a8bc00,0xb9a88000,0xb9a83c00,0x39a80000,0x39a8bc00,0xb9a88000,0xb9a83c00,
0xbbd98000,0x3aa7361f,0xb872b9a8,0x323e3b64,0xb23e3c00,0x3872bb64,0xbaa739a8,0x3bd9b61f,0xb23e3c00,0x3872bb64,0xbaa739a8,0x3bd9b61f,0x3bd98000,0xbaa7b61f,0x387239a8,0xb23ebb64,
0x361fbc00,0xbb6439a8,0x3b640000,0xb61fb9a8,0xb61f3c00,0x3b64b9a8,0xbb648000,0x361f39a8,0xbb648000,0x361f39a8,0x361fbc00,0xbb6439a8,0x3b648000,0xb61fb9a8,0xb61f3c00,0x3b64b9a8,
0x38728000,0x3bd93b64,0x323e39a8,0xbaa7b61f,0xbaa7bc00,0x323eb61f,0x3bd939a8,0x38723b64,0x3aa73c00,0xb23e361f,0xbbd9b9a8,0xb872bb64,0x38728000,0x3bd93b64,0x323e39a8,0xbaa7b61f,
0x39a88000,0x39a83c00,0xb9a88000,0xb9a8bc00,0x39a80000,0x39a83c00,0xb9a80000,0xb9a8bc00,0x39a83c00,0xb9a88000,0xb9a8bc00,0x39a88000,0x39a83c00,0xb9a88000,0xb9a8bc00,0x39a80000,
0x3bd93c00,0x3aa73b64,0x387239a8,0x323e361f,0x323e8000,0x3872361f,0x3aa739a8,0x3bd93b64,0xb23e8000,0xb872b61f,0xbaa7b9a8,0xbbd9bb64,0x3bd93c00,0x3aa73b64,0x387239a8,0x323e361f,
0xb61f8000,0xbb64b9a8,0xbb64bc00,0xb61fb9a8,0x361f8000,0x3b6439a8,0x3b643c00,0x361f39a8,0xbb64bc00,0xb61fb9a8,0x361f0000,0x3b6439a8,0x3b643c00,0x361f39a8,0xb61f8000,0xbb64b9a8,
0x0,0x0,0x0,0x0,0x0,0x0,0x0,0x0,0x3c003c00,0x3c003c00,0x3c003c00,0x3c003c00,0x3c003c00,0x3c003c00,0x3c003c00,0x3c003c00,
0x323e0000,0x3872361f,0x3aa739a8,0x3bd93b64,0x3bd93c00,0x3aa73b64,0x387239a8,0x323e361f,0x3bd93c00,0x3aa73b64,0x387239a8,0x323e361f,0xb23e0000,0xb872b61f,0xbaa7b9a8,0xbbd9bb64,
0xb61f0000,0xbb64b9a8,0xbb64bc00,0xb61fb9a8,0x361f0000,0x3b6439a8,0x3b643c00,0x361f39a8,0xbb64bc00,0xb61fb9a8,0x361f8000,0x3b6439a8,0x3b643c00,0x361f39a8,0xb61f0000,0xbb64b9a8,
0xbaa7bc00,0x323eb61f,0x3bd939a8,0x38723b64,0x38720000,0x3bd93b64,0x323e39a8,0xbaa7b61f,0x38728000,0x3bd93b64,0x323e39a8,0xbaa7b61f,0x3aa73c00,0xb23e361f,0xbbd9b9a8,0xb872bb64,
0x3c00,0x8000bc00,0x3c00,0x8000bc00,0x3c00,0x8000bc00,0x80003c00,0x8000bc00,0x3c000000,0xbc000000,0x3c008000,0xbc000000,0x3c008000,0xbc000000,0x3c008000,0xbc000000,
0xb23e3c00,0x3872bb64,0xbaa739a8,0x3bd9b61f,0xbbd90000,0x3aa7361f,0xb872b9a8,0x323e3b64,0x3bd90000,0xbaa7b61f,0x387239a8,0xb23ebb64,0xb23e3c00,0x3872bb64,0xbaa739a8,0x3bd9b61f,
0x361fbc00,0xbb6439a8,0x3b648000,0xb61fb9a8,0xb61f3c00,0x3b64b9a8,0xbb640000,0x361f39a8,0xbb640000,0x361f39a8,0x361fbc00,0xbb6439a8,0x3b640000,0xb61fb9a8,0xb61f3c00,0x3b64b9a8,
0x3aa78000,0x323ebb64,0xbbd939a8,0x3872361f,0xb8723c00,0x3bd9b61f,0xb23eb9a8,0xbaa73b64,0x3872bc00,0xbbd9361f,0x323e39a8,0x3aa7bb64,0x3aa70000,0x323ebb64,0xbbd939a8,0x3872361f,
0xb23e0000,0xb872361f,0xbaa739a8,0xbbd93b64,0xbbd93c00,0xbaa73b64,0xb87239a8,0xb23e361f,0xbbd93c00,0xbaa73b64,0xb87239a8,0xb23e361f,0x323e8000,0x3872b61f,0x3aa7b9a8,0x3bd9bb64,
0x0,0x8000,0x8000,0x8000,0x8000,0x8000,0x80008000,0x8000,0xbc003c00,0xbc003c00,0xbc003c00,0xbc003c00,0xbc003c00,0xbc003c00,0xbc003c00,0xbc003c00,
0x3aa7bc00,0xb23eb61f,0xbbd939a8,0xb8723b64,0xb8720000,0xbbd93b64,0xb23e39a8,0x3aa7b61f,0xb8728000,0xbbd93b64,0xb23e39a8,0x3aa7b61f,0xbaa73c00,0x323e361f,0x3bd9b9a8,0x3872bb64,
0x361f0000,0x3b64b9a8,0x3b64bc00,0x361fb9a8,0xb61f0000,0xbb6439a8,0xbb643c00,0xb61f39a8,0x3b64bc00,0x361fb9a8,0xb61f8000,0xbb6439a8,0xbb643c00,0xb61f39a8,0x361f0000,0x3b64b9a8,
0x323e3c00,0xb872bb64,0x3aa739a8,0xbbd9b61f,0x3bd98000,0xbaa7361f,0x3872b9a8,0xb23e3b64,0xbbd90000,0x3aa7b61f,0xb87239a8,0x323ebb64,0x323e3c00,0xb872bb64,0x3aa739a8,0xbbd9b61f,
0x80003c00,0xbc00,0x80003c00,0x8000bc00,0x80003c00,0xbc00,0x80003c00,0xbc00,0xbc000000,0x3c000000,0xbc008000,0x3c000000,0xbc008000,0x3c000000,0xbc008000,0x3c008000,
0xbaa78000,0xb23ebb64,0x3bd939a8,0xb872361f,0x38723c00,0xbbd9b61f,0x323eb9a8,0x3aa73b64,0xb872bc00,0x3bd9361f,0xb23e39a8,0xbaa7bb64,0xbaa70000,0xb23ebb64,0x3bd939a8,0xb872361f,
0xb61fbc00,0x3b6439a8,0xbb640000,0x361fb9a8,0x361f3c00,0xbb64b9a8,0x3b648000,0xb61f39a8,0x3b648000,0xb61f39a8,0xb61fbc00,0x3b6439a8,0xbb640000,0x361fb9a8,0x361f3c00,0xbb64b9a8,
0x39a80000,0x39a83c00,0xb9a80000,0xb9a8bc00,0x39a88000,0x39a83c00,0xb9a80000,0xb9a8bc00,0x39a83c00,0xb9a80000,0xb9a8bc00,0x39a88000,0x39a83c00,0xb9a80000,0xb9a8bc00,0x39a88000,
0x3aa70000,0x323e3b64,0xbbd9b9a8,0x3872b61f,0x38723c00,0xbbd9b61f,0x323eb9a8,0x3aa73b64,0x38723c00,0xbbd9b61f,0x323eb9a8,0x3aa73b64,0xbaa70000,0xb23ebb64,0x3bd939a8,0xb872361f,
0xbb640000,0x361fb9a8,0x361f3c00,0xbb64b9a8,0x3b640000,0xb61f39a8,0xb61fbc00,0x3b6439a8,0xb61fbc00,0x3b6439a8,0xbb640000,0x361fb9a8,0x361f3c00,0xbb64b9a8,0x3b648000,0xb61f39a8,
0xb23ebc00,0x38723b64,0xbaa7b9a8,0x3bd9361f,0x3bd90000,0xbaa7361f,0x3872b9a8,0xb23e3b64,0x3bd98000,0xbaa7361f,0x3872b9a8,0xb23e3b64,0x323e3c00,0xb872bb64,0x3aa739a8,0xbbd9b61f,
0xb9a83c00,0x39a88000,0x39a8bc00,0xb9a80000,0xb9a83c00,0x39a88000,0x39a8bc00,0xb9a88000,0x39a80000,0x39a8bc00,0xb9a80000,0xb9a83c00,0x39a88000,0x39a8bc00,0xb9a80000,0xb9a83c00,
0xbaa73c00,0x323e361f,0x3bd9b9a8,0x3872bb64,0xb8728000,0xbbd93b64,0xb23e39a8,0x3aa7b61f,0x38720000,0x3bd9bb64,0x323eb9a8,0xbaa7361f,0xbaa73c00,0x323e361f,0x3bd9b9a8,0x3872bb64,
0x3b64bc00,0x361fb9a8,0xb61f8000,0xbb6439a8,0xbb643c00,0xb61f39a8,0x361f8000,0x3b64b9a8,0xb61f0000,0xbb6439a8,0xbb643c00,0xb61f39a8,0x361f0000,0x3b64b9a8,0x3b64bc00,0x361fb9a8,
0x323e8000,0x3872b61f,0x3aa7b9a8,0x3bd9bb64,0xbbd93c00,0xbaa73b64,0xb87239a8,0xb23e361f,0x3bd9bc00,0x3aa7bb64,0x3872b9a8,0x323eb61f,0x323e0000,0x3872b61f,0x3aa7b9a8,0x3bd9bb64,
0xbaa70000,0xb23e3b64,0x3bd9b9a8,0xb872b61f,0xb8723c00,0x3bd9b61f,0xb23eb9a8,0xbaa73b64,0xb8723c00,0x3bd9b61f,0xb23eb9a8,0xbaa73b64,0x3aa78000,0x323ebb64,0xbbd939a8,0x3872361f,
0xb9a80000,0xb9a83c00,0x39a80000,0x39a8bc00,0xb9a88000,0xb9a83c00,0x39a80000,0x39a8bc00,0xb9a83c00,0x39a80000,0x39a8bc00,0xb9a88000,0xb9a83c00,0x39a88000,0x39a8bc00,0xb9a88000,
0x323ebc00,0xb8723b64,0x3aa7b9a8,0xbbd9361f,0xbbd90000,0x3aa7361f,0xb872b9a8,0x323e3b64,0xbbd98000,0x3aa7361f,0xb872b9a8,0x323e3b64,0xb23e3c00,0x3872bb64,0xbaa739a8,0x3bd9b61f,
0x3b640000,0xb61fb9a8,0xb61f3c00,0x3b64b9a8,0xbb640000,0x361f39a8,0x361fbc00,0xbb6439a8,0x361fbc00,0xbb6439a8,0x3b640000,0xb61fb9a8,0xb61f3c00,0x3b64b9a8,0xbb648000,0x361f39a8,
0x3aa73c00,0xb23e361f,0xbbd9b9a8,0xb872bb64,0x38728000,0x3bd93b64,0x323e39a8,0xbaa7b61f,0xb8720000,0xbbd9bb64,0xb23eb9a8,0x3aa7361f,0x3aa73c00,0xb23e361f,0xbbd9b9a8,0xb872bb64,
0x39a83c00,0xb9a88000,0xb9a8bc00,0x39a88000,0x39a83c00,0xb9a88000,0xb9a8bc00,0x39a80000,0xb9a80000,0xb9a8bc00,0x39a80000,0x39a83c00,0xb9a88000,0xb9a8bc00,0x39a88000,0x39a83c00,
0xb23e8000,0xb872b61f,0xbaa7b9a8,0xbbd9bb64,0x3bd93c00,0x3aa73b64,0x387239a8,0x323e361f,0xbbd9bc00,0xbaa7bb64,0xb872b9a8,0xb23eb61f,0xb23e0000,0xb872b61f,0xbaa7b9a8,0xbbd9bb64,
0xbb64bc00,0xb61fb9a8,0x361f0000,0x3b6439a8,0x3b643c00,0x361f39a8,0xb61f8000,0xbb64b9a8,0x361f0000,0x3b6439a8,0x3b643c00,0x361f39a8,0xb61f0000,0xbb64b9a8,0xbb64bc00,0xb61fb9a8,
};
__device__ __align__(1024) bf16 g_x1T[DM * XP];
__device__ __align__(1024) bf16 g_x2T[DM * XP];
__device__ __align__(1024) float g_sums[2][SEQ];

#define TS_DECL
#define TS_ARG
#define TS_PASS
#define TS(i)
#define TSX(row, i)
#define TS_BEGIN
#define TS_END(slot)

__device__ __align__(1024) uint32_t g_keo[DM / 2][2048];
__device__ __align__(128) uint32_t g_ksc[DM];

struct cplx { float r, i; };
__device__ __forceinline__ cplx cmul(cplx a, cplx b) {
    cplx o;
    o.r = fmaf(a.r, b.r, -a.i * b.i);
    o.i = fmaf(a.r, b.i, a.i * b.r);
    return o;
}
__device__ __forceinline__ cplx csq(cplx a) {
    cplx o;
    o.r = fmaf(a.r, a.r, -a.i * a.i);
    o.i = 2.f * a.r * a.i;
    return o;
}
__device__ __forceinline__ cplx cexp_p(float arl, float ai, float p) {
    float mag = ex2(arl * p);
    float ang = ai * p;
    float n = rintf(ang * 0.15915494309189535f);
    float r = fmaf(n, -6.2831854820251465f, ang);
    r = fmaf(n, 1.7484555e-7f, r);
    cplx o;
    o.r = mag * __cosf(r);
    o.i = mag * __sinf(r);
    return o;
}

__device__ __forceinline__ uint32_t pack2h(float lo, float hi) {
    uint32_t r;
    asm("cvt.rn.f16x2.f32 %0, %1, %2;" : "=r"(r) : "f"(hi), "f"(lo));
    return r;
}
__device__ __forceinline__ uint32_t hmul(uint32_t a, uint32_t b) { uint32_t d; asm("mul.rn.f16x2 %0, %1, %2;" : "=r"(d) : "r"(a), "r"(b)); return d; }
__device__ __forceinline__ uint32_t hfma(uint32_t a, uint32_t b, uint32_t c) { uint32_t d; asm("fma.rn.f16x2 %0, %1, %2, %3;" : "=r"(d) : "r"(a), "r"(b), "r"(c)); return d; }
__device__ __forceinline__ uint32_t hfms(uint32_t a, uint32_t b, uint32_t c) {
    uint32_t d;
    asm("{\n.reg .b32 n;\nneg.f16x2 n, %1;\nfma.rn.f16x2 %0, n, %2, %3;\n}" : "=r"(d) : "r"(a), "r"(b), "r"(c));
    return d;
}
__device__ __forceinline__ uint32_t hadd(uint32_t a, uint32_t b) { uint32_t d; asm("add.rn.f16x2 %0, %1, %2;" : "=r"(d) : "r"(a), "r"(b)); return d; }
__device__ __forceinline__ uint32_t hsub(uint32_t a, uint32_t b) { uint32_t d; asm("sub.rn.f16x2 %0, %1, %2;" : "=r"(d) : "r"(a), "r"(b)); return d; }
__device__ __forceinline__ uint4 ldg_tab(int tab, int t) { return __ldg((const uint4*)c_fft + tab * 128 + t); }
__device__ __forceinline__ uint32_t u4(const uint4& v, int i) { return i == 0 ? v.x : i == 1 ? v.y : i == 2 ? v.z : v.w; }
struct cpair { uint32_t r, i; };
__device__ __forceinline__ cpair pmul(cpair p, uint32_t z) {
    const __half2 zv = *reinterpret_cast<const __half2*>(&z), pr = *reinterpret_cast<const __half2*>(&p.r), pi = *reinterpret_cast<const __half2*>(&p.i);
    const __half2 zr = __low2half2(zv), zi = __high2half2(zv);
    const __half2 a = __hfma2(__hneg2(pi), zi, __hmul2(pr, zr)), b = __hfma2(pi, zr, __hmul2(pr, zi));
    return {*reinterpret_cast<const uint32_t*>(&a), *reinterpret_cast<const uint32_t*>(&b)};
}
__device__ __forceinline__ uint32_t packz(cplx z) { return pack2h(z.r, z.i); }
__device__ __forceinline__ void wgmma_kg(float (&d)[24], uint64_t da, uint64_t db, int scale_d) {
    asm volatile("{\n.reg .pred p;\nsetp.ne.b32 p, %26, 0;\n"
                 "wgmma.mma_async.sync.aligned.m64n48k16.f32.f16.f16 "
                 "{%0,%1,%2,%3,%4,%5,%6,%7,%8,%9,%10,%11,%12,%13,%14,%15,%16,%17,%18,%19,%20,%21,%22,%23}, %24, %25, p, 1, 1, 1, 1;\n}\n"
                 : "+f"(d[0]), "+f"(d[1]), "+f"(d[2]), "+f"(d[3]), "+f"(d[4]), "+f"(d[5]), "+f"(d[6]), "+f"(d[7]), "+f"(d[8]), "+f"(d[9]),
                   "+f"(d[10]), "+f"(d[11]), "+f"(d[12]), "+f"(d[13]), "+f"(d[14]), "+f"(d[15]), "+f"(d[16]), "+f"(d[17]), "+f"(d[18]), "+f"(d[19]),
                   "+f"(d[20]), "+f"(d[21]), "+f"(d[22]), "+f"(d[23])
                 : "l"(da), "l"(db), "r"(scale_d));
}

struct SsmParams { const bf16 *lar, *aim, *cre, *cim, *logdt, *dskip; };
constexpr int KG_TABLES = 6 * 16384, KG_DUMP = 6 * 3072;
struct KgShared { uint32_t kmax[5]; };
struct KgParams { uint32_t l[3], a[3], r[3], i[3], dt; };

__device__ __forceinline__ void kgen_load(KgParams& kp, int d0, int warp, int lane, const SsmParams& sp) {
    const int d = d0 + (warp < 8 ? 2 * (warp >> 2) + (warp & 1) : 4), idx = d * (NMODE / 2) + lane;
    const bf16 *pr = (warp & 2) ? sp.cre : sp.lar, *pi = (warp & 2) ? sp.cim : sp.aim;
#pragma unroll
    for (int j = 0; j < 3; j++) {
        kp.l[j] = __ldg((const uint32_t*)sp.lar + idx + 32 * j); kp.a[j] = __ldg((const uint32_t*)sp.aim + idx + 32 * j);
        kp.r[j] = __ldg((const uint32_t*)pr + idx + 32 * j); kp.i[j] = __ldg((const uint32_t*)pi + idx + 32 * j);
    }
    kp.dt = __ldg((const uint16_t*)sp.logdt + d);
}

struct KgAnchors { uint32_t v[8]; };
__device__ __forceinline__ KgAnchors kg_anchor_lo(const KgParams& kp, uint32_t sel, float dt) {
    auto B = [&](uint32_t v) { return __uint_as_float(__byte_perm(v, 0u, sel)); };
    const float arl = -rbf(ex2(B(kp.l[0]) * 1.4426950408889634f)) * dt * 1.4426950408889634f, ai = B(kp.a[0]) * dt;
    const cplx z8 = cexp_p(arl, ai, 8.f), z16 = csq(z8), z24 = cmul(z16, z8), z32 = csq(z16), z64 = csq(z32), z128 = csq(z64), z192 = cmul(z128, z64);
    return {{pack2h(1.f, z8.r), pack2h(0.f, z8.i), pack2h(z16.r, z24.r), pack2h(z16.i, z24.i), packz(z32), packz(z64), packz(z128), packz(z192)}};
}
__device__ __forceinline__ KgAnchors kg_anchor_hi(const KgParams& kp, uint32_t sel, float dt, float cs) {
    auto B = [&](uint32_t v) { return __uint_as_float(__byte_perm(v, 0u, sel)); };
    const float arl = -rbf(ex2(B(kp.l[0]) * 1.4426950408889634f)) * dt * 1.4426950408889634f, ai = B(kp.a[0]) * dt;
    const cplx z1 = cexp_p(arl, -ai, 1.f), z2 = csq(z1), z4 = csq(z2), z256 = cexp_p(arl, -ai, 256.f), z512 = csq(z256), z1024 = csq(z512);
    const cplx H0 = {B(kp.r[0]) * cs, -B(kp.i[0]) * cs}, H4 = cmul(H0, z4);
    return {{pack2h(H0.r, H4.r), pack2h(H0.i, H4.i), packz(z1), packz(z2), packz(z256), packz(z512), packz(z1024), 0u}};
}

__device__ __forceinline__ void kgen_tables(KgParams& kp, uint32_t scr, uint32_t dump, int warp, int lane TS_ARG) {
    const int wg = warp >> 2, half = warp & 1, sw = lane & 7;
    const bool hi = warp & 2;
    TS(23);
    const float dt = rbf(ex2(bf_lo(kp.dt) * 1.4426950408889634f));
    uint32_t sel = (wg == 2 && half) ? 0x3244u : 0x1044u;
    float cs = 0.f;
    KgAnchors an;
    if (hi) {
        uint32_t m = 0;
#pragma unroll
        for (int j = 0; j < 3; j++) m = __vmaxu2(m, __vmaxu2(kp.r[j] & 0x7FFF7FFFu, kp.i[j] & 0x7FFF7FFFu));
        m = __reduce_max_sync(~0u, max(m << 16, m & 0xFFFF0000u));
        const uint32_t e = min(max(__float_as_uint(2.f * dt * __uint_as_float(m)) >> 23, 2u), 252u);
        cs = 2.f * dt * __uint_as_float((253u - e) << 23);
        if (lane == 0) sts32(dump + (2 * wg + half) * 3072, (e + 1u) << 23);
        an = kg_anchor_hi(kp, sel, dt, cs);
    } else {
        an = kg_anchor_lo(kp, sel, dt);
    }
    float acc[24];
    const int nstep = wg == 2 ? 3 : 6;
#pragma unroll 1
    for (int c = 0; c < nstep; c++) {
        if (wg < 2) sel ^= 0x2200u;
        if (wg == 2 || (c & 1)) {
#pragma unroll
            for (int j = 0; j < 2; j++) { kp.l[j] = kp.l[j + 1]; kp.a[j] = kp.a[j + 1]; kp.r[j] = kp.r[j + 1]; kp.i[j] = kp.i[j + 1]; }
        }
        const uint32_t buf = scr + (2 * wg + (c & 1)) * 16384, tb = buf + lane * 128;
        if (!hi) {
            cpair p[4];
            p[0] = {an.v[0], an.v[1]}; p[1] = {an.v[2], an.v[3]};
            p[2] = pmul(p[0], an.v[4]); p[3] = pmul(p[1], an.v[4]);
#pragma unroll
            for (int j = 0; j < 4; j++) {
                cpair v[4];
#pragma unroll
                for (int i = 0; i < 4; i++) v[i] = j ? pmul(p[i], an.v[4 + j]) : p[i];
                const uint32_t a = tb + (((4 * half + j) ^ sw) << 4);
                sts128(a, make_uint4(v[0].r, v[1].r, v[2].r, v[3].r));
                sts128(a + 4096, make_uint4(v[0].i, v[1].i, v[2].i, v[3].i));
            }
            an = kg_anchor_lo(kp, sel, dt);
        } else {
            const uint32_t h1 = an.v[2], h2 = an.v[3], h256 = an.v[4], h512 = an.v[5], h1024 = an.v[6];
            cpair p[11];
            p[0] = {an.v[0], an.v[1]};
            p[1] = pmul(p[0], h2); p[2] = pmul(p[0], h1); p[3] = pmul(p[1], h1);
            p[4] = pmul(p[0], h256); p[5] = pmul(p[1], h256); p[6] = pmul(p[0], h512); p[7] = pmul(p[4], h512);
            p[8] = pmul({__byte_perm(p[0].r, p[4].r, 0x5410), __byte_perm(p[0].i, p[4].i, 0x5410)}, h1024);
            p[9] = pmul(p[8], h512); p[10] = pmul(p[8], h1024);
#pragma unroll
            for (int j = 0; j < 3; j++) {
                const uint32_t a = tb + 8192 + (((3 * half + j) ^ sw) << 4);
                sts128(a, make_uint4(p[4 * j].r, p[4 * j + 1].r, p[4 * j + 2].r, p[j < 2 ? 4 * j + 3 : 10].r));
                sts128(a + 4096, make_uint4(p[4 * j].i, p[4 * j + 1].i, p[4 * j + 2].i, p[j < 2 ? 4 * j + 3 : 10].i));
            }
            an = kg_anchor_hi(kp, sel, dt, cs);
        }
        if (c == 0) TS(24);
        if (c == 2) TS(26);
        fence_async_smem();
        wg_wait<0>();
        named_bar(5 + wg, 128);
        if (c == 1) TS(25);
        if (c == 2) TS(28);
        const uint64_t da = mkdesc(buf, 4096, 1024, 1);
        wg_fence();
#pragma unroll
        for (int k = 0; k < 4; k++) wgmma_kg(acc, da + k * 128, da + 512 + k * 128, k > 0 || c > 0);
        wg_commit();
    }
    const uint32_t ob = dump + (2 * wg + (hi ? 1 : 0)) * 3072, o = ob + ((16 * half + (lane >> 2)) * 24 + 2 * (lane & 3)) * 4;
    const float ci = __uint_as_float(lds32(ob));
    named_bar(5 + wg, 128);
    wg_wait<0>();
#pragma unroll
    for (int j = 0; j < 3; j++)
#pragma unroll
        for (int h = 0; h < 2; h++)
            asm volatile("st.shared.v2.f32 [%0], {%1, %2};" ::"r"(o + h * 768 + j * 32), "f"(ci * (hi ? acc[12 + 4 * j + 2 * h] : acc[4 * j + 2 * h])),
                         "f"(ci * (hi ? acc[13 + 4 * j + 2 * h] : acc[4 * j + 2 * h + 1])) : "memory");
}

__device__ __forceinline__ void kgen_expand(int d0, uint32_t dump, KgShared* ks, int ht, const SsmParams& sp TS_ARG) {
    const int lane = ht & 31;
    auto F = [](uint32_t x) { return __uint_as_float(x); };
#pragma unroll 1
    for (int c = 0; c < 5; c++) {
        const float dsk = ht ? 0.f : __bfloat162float(sp.dskip[d0 + c]);
        float m = 0.f;
#pragma unroll
        for (int i = 0; i < 2; i++) {
            const uint32_t a = dump + c * 3072 + (ht + 96 * i) * 16;
            const uint4 x = lds128(a), y = c == 4 ? lds128(a + 3072) : make_uint4(0, 0, 0, 0);
            const float v0 = F(x.x) + F(y.x) + (i ? 0.f : dsk), v1 = F(x.y) + F(y.y), v2 = F(x.z) + F(y.z), v3 = F(x.w) + F(y.w);
            sts128(a, make_uint4(__float_as_uint(v0), __float_as_uint(v1), __float_as_uint(v2), __float_as_uint(v3)));
            m = fmaxf(fmaxf(m, fmaxf(fabsf(v0), fabsf(v1))), fmaxf(fabsf(v2), fabsf(v3)));
        }
        const uint32_t mm = __reduce_max_sync(~0u, __float_as_uint(m));
        if (lane == 0) atomicMax(&ks->kmax[c], mm);
    }
    named_bar(4, 96);
    TSX(2, 6);
#pragma unroll 1
    for (int task = ht >> 5; task < 20; task += 3) {
        const int c = task >> 2, it = (task & 3) * 32 + lane, a = it >> 2, d = d0 + c;
        const uint4 o0 = ldg_tab(16, it), o1 = ldg_tab(17, it);
        const uint32_t e = min(max(ks->kmax[c] >> 23, 4u), 250u), b = dump + c * 3072;
        const float sc = __uint_as_float((253u - e) << 23);
        if (it == 0) g_ksc[d] = e;
        uint32_t ev[4], ov[4];
#pragma unroll
        for (int i = 0; i < 4; i++) {
            const float x0 = F(lds32(b + (u4(o0, i) & 0xFFFF))), x1 = F(lds32(b + (u4(o0, i) >> 16)));
            const float y0 = F(lds32(b + (u4(o1, i) & 0xFFFF))), y1 = F(lds32(b + (u4(o1, i) >> 16)));
            ev[i] = pack2h((x0 + y0) * sc, (x1 + y1) * sc);
            ov[i] = pack2h((x0 - y0) * sc, (x1 - y1) * sc);
        }
        uint32_t* dst = &g_keo[d >> 1][a * 32 + (((4 * (d & 1) + (it & 3)) ^ (a & 7)) << 2)];
        stg128(dst, make_uint4(ev[0], ev[1], ev[2], ev[3]));
        stg128(dst + 1024, make_uint4(ov[0], ov[1], ov[2], ov[3]));
    }
}
#define Q_SCHED 0
#define Q_WAITFOR(it) (Q_SCHED == 0 ? (it) - 2 : Q_SCHED == 1 ? ((it) == 3 ? 1 : 0) : Q_SCHED == 2 ? -1 : (it) - 1)
#define Q_S0 6
#define Q_WGATE 0
#define Q_PREW 1
constexpr int Q_ST = 4;
constexpr int Q_AB = 16384, Q_BB = 30720, Q_SB = Q_AB + Q_BB;
constexpr int Q_EROW = 336;
constexpr int Q_ESLOT = 8 * Q_EROW;
constexpr int Q_EOFF = Q_ST * Q_SB;
constexpr int Q_KG = 2 * Q_SB;
constexpr int Q_KDUMP = Q_EOFF + 7 * Q_ESLOT;
static_assert(Q_KG + KG_TABLES <= Q_KDUMP, "kernel generation layout");
constexpr int Q_SMEM = Q_KDUMP + KG_DUMP + 1024;
__host__ __device__ constexpr int w_main(int j) { return (2 + (j >> 2)) * Q_SB + (j & 3) * 10240; }
__host__ __device__ constexpr int w_rem(int j) { return j < 4 ? (2 + (j >> 1)) * Q_SB + 40960 + (j & 1) * 2560 : 20480 + (j - 4) * 2560; }
constexpr int W_RES = 0, W_OUT = Q_SB;

__device__ unsigned g_epoch;
__device__ __align__(1024) unsigned long long g_stats[SEQ];
__device__ __align__(1024) uint4 g_csp[8][16][80];
__device__ __align__(1024) float g_colsum[3 * DM];
__device__ __align__(1024) uint4 g_halo[128][2][7][32];
__device__ __align__(1024) uint4 g_of[16][8][8][5][32];

__device__ __forceinline__ unsigned long long ld_ll(const unsigned long long* p) {
    unsigned long long v;
    asm volatile("ld.relaxed.gpu.global.b64 %0, [%1];" : "=l"(v) : "l"(p) : "memory");
    return v;
}
__device__ __forceinline__ void st_ll(unsigned long long* p, uint32_t payload, uint32_t tag) {
    const unsigned long long v = (unsigned long long)payload | ((unsigned long long)tag << 32);
    asm volatile("st.relaxed.gpu.global.b64 [%0], %1;" ::"l"(p), "l"(v) : "memory");
}
__device__ __forceinline__ uint4 ld_ll4(const uint4* p) {
    uint4 v;
    asm volatile("{\n.reg .b128 t;\n.reg .b64 a, b;\nld.relaxed.gpu.global.b128 t, [%4];\nmov.b128 {a, b}, t;\nmov.b64 {%0, %1}, a;\nmov.b64 {%2, %3}, b;\n}"
                 : "=r"(v.x), "=r"(v.y), "=r"(v.z), "=r"(v.w) : "l"(p) : "memory");
    return v;
}
__device__ __forceinline__ void st_ll4(uint4* p, uint32_t x, uint32_t y, uint32_t z, uint32_t w) {
    asm volatile("{\n.reg .b128 t;\n.reg .b64 a, b;\nmov.b64 a, {%1, %2};\nmov.b64 b, {%3, %4};\nmov.b128 t, {a, b};\nst.relaxed.gpu.global.b128 [%0], t;\n}"
                 ::"l"(p), "r"(x), "r"(y), "r"(z), "r"(w) : "memory");
}

__global__ void __launch_bounds__(384, 1)
attn_kernel(const __grid_constant__ CUtensorMap mX, const __grid_constant__ CUtensorMap mW, const __grid_constant__ CUtensorMap mWr,
            const __grid_constant__ CUtensorMap mWo, const __grid_constant__ CUtensorMap mWor, const __grid_constant__ CUtensorMap mRes,
            const __grid_constant__ CUtensorMap mOut, const bf16* xin, const bf16* __restrict__ wqkv, const bf16* __restrict__ wo,
            float* sums, const SsmParams sp, int layer, int slot) {
    extern __shared__ __align__(1024) char smraw[];
    __shared__ __align__(8) uint64_t s_full[Q_ST], s_empty[Q_ST], s_wfull[3], s_ex[8], s_res, s_go, s_qdone, s_att, s_prep;
    __shared__ __align__(16) float s_cs[240], s_mean[2][72], s_rstd[2][72], s_red[3][32];
    __shared__ KgShared s_kg;
    const uint32_t sb = (s2u(smraw) + 1023) & ~1023u;
    const int tid = threadIdx.x, warp = __shfl_sync(~0u, tid >> 5, 0), lane = tid & 31;
    const int rank = blockIdx.x & 1, blk = blockIdx.x & 15, hg = blockIdx.x >> 4;
    const int g = lane >> 2, q = lane & 3;
    TS_DECL;
    TS_BEGIN;
    KgParams kp;
    if (layer == 0) kgen_load(kp, blockIdx.x * 5, warp, lane, sp);
    if (tid < 5) s_kg.kmax[tid] = 0u;
    if (tid == 256) { prefetch_tmap(&mW); prefetch_tmap(&mWr); prefetch_tmap(&mX); }
    if (tid == 288) { prefetch_tmap(&mWo); prefetch_tmap(&mWor); prefetch_tmap(&mRes); prefetch_tmap(&mOut); }
    if (tid == 0) {
        for (int i = 0; i < Q_ST; i++) { mbar_init(s2u(&s_full[i]), 1); mbar_init(s2u(&s_empty[i]), 16); }
        for (int i = 0; i < 3; i++) mbar_init(s2u(&s_wfull[i]), 1);
        fence_mbar_init();
    }
    if (tid == 32) {
        for (int i = 0; i < 8; i++) mbar_init(s2u(&s_ex[i]), 1);
        mbar_init(s2u(&s_res), 1); mbar_init(s2u(&s_go), 4); mbar_init(s2u(&s_qdone), 8); mbar_init(s2u(&s_att), 4); mbar_init(s2u(&s_prep), 96);
        fence_mbar_init();
    }
    __syncthreads();
    cluster_arrive_relaxed();
    cluster_wait();

    auto issue_w = [&](int it) {
        const int s = it & (Q_ST - 1);
        const uint32_t fb = s2u(&s_full[s]), db = sb + s * Q_SB + Q_AB + rank * 15360;
        const int k0 = it * 64 + rank * 32;
        mbar_expect(fb, Q_SB);
#pragma unroll
        for (int p = 0; p < 3; p++) tma2d_mc(db + p * 4096, &mW, p * DM + hg * 80, k0, fb, 3);
        tma3d_mc(db + 12288, &mWr, hg * 80 + 64, k0, 0, fb, 3);
    };
    auto issue_x = [&](int it) {
        const int s = it & (Q_ST - 1);
        tma3d(sb + s * Q_SB, &mX, (layer ? blk : it) * 64, (layer ? it : blk) * 64, 0, s2u(&s_full[s]));
    };
    if (layer == 0) {
        if (warp == 8) {
            if (elect_one()) {
#pragma unroll 1
                for (int it = 0; it < 2; it++) { issue_w(it); issue_x(it); }
            }
            __syncwarp();
        }
        kgen_tables(kp, sb + Q_KG, sb + Q_KDUMP, warp, lane TS_PASS);
        if (warp <= 8) asm volatile("bar.arrive 8, 384;" ::: "memory");
        fence_async_smem();
        cluster_arrive_relaxed();
        TS(1);
    }

    if (warp >= 8) {
        asm volatile("setmaxnreg.dec.sync.aligned.u32 72;");
        if (warp == 8) {
            if (layer == 0) cluster_wait();
            if (elect_one()) {
                if (layer) {
#pragma unroll 1
                    for (int it = 0; it < Q_PREW; it++) issue_w(it);
                    pdl_wait();
                }
#pragma unroll 1
                for (int it = layer ? 0 : 2; it < 10; it++) {
                    if (it >= Q_ST) mbar_wait(s2u(&s_empty[it & (Q_ST - 1)]), ((it >> 2) - 1) & 1);
                    else if (it > 0 && Q_WAITFOR(it) >= 0) mbar_wait(s2u(&s_full[Q_WAITFOR(it)]), 0);
                    issue_x(it);
                    if (it >= Q_PREW || layer == 0) issue_w(it);
                }
#pragma unroll 1
                for (int b = 0; b < 3; b++) {
                    const uint32_t fb = s2u(&s_wfull[b]);
                    mbar_wait(s2u(&s_empty[(2 + b) & 3]), b < 2);
                    TS(11 + b);
                    if (b == 2) {
                        mbar_expect(s2u(&s_res), 20480);
                        if (layer == 0) tma3d(sb + W_RES, &mX, hg * 80, blk * 64, 0, s2u(&s_res));
                        tma3d(sb + W_RES + (layer ? 0 : 16384), &mRes, layer ? blk * 64 : hg * 80 + 64, layer ? hg * 80 : blk * 64, 0, s2u(&s_res));
                    }
                    mbar_expect(fb, b < 2 ? 46080 : 10240);
#pragma unroll 1
                    for (int i = 0; i < 4; i++) {
                        if (b < 2) tma2d_mc(sb + w_main(4 * b) + i * 10240 + rank * 5120, &mWo, hg * 80, ((hg + 4 * b + i) & 7) * 80 + rank * 40, fb, 3);
                        if (b == 2 || i < 2) tma2d_mc(sb + w_rem(2 * b) + i * 2560 + rank * 1280, &mWor, hg * 80 + 64, ((hg + 2 * b + i) & 7) * 80 + rank * 40, fb, 3);
                    }
                }
            }
            __syncwarp();
        } else {
            const int ht = tid - 288, hw = warp - 9;
            const int srow = 1024 * (hg >> 2) + 64 * blk + 16 * (hg & 3);
            auto F = [](uint32_t x) { return __uint_as_float(x); };
            pdl_wait();
            if (layer) pdl_launch();
            const uint32_t tag = 2u * ldg32(&g_epoch) + layer + 1u;
            if (layer) mbar_wait(s2u(&s_full[1]), 0);
            if (ht == 0) TSX(2, 2);
            if (layer == 0) {
                if (ht < 50) asm volatile("prefetch.global.L2 [%0];" ::"l"((const char*)wo + (size_t)(blockIdx.x * 50 + ht) * 128));
                if (ht >= 64 && ht < 67 && blockIdx.x * 3 + ht - 64 < sizeof(c_fft) / 128)
                    asm volatile("prefetch.global.L2 [%0];" ::"l"((const char*)c_fft + (size_t)(blockIdx.x * 3 + ht - 64) * 128));
                const bf16* wsrc = wqkv + (size_t)(40 * blk + hw) * (3 * DM) + (min(lane, 29) / 10) * DM + hg * 80 + 8 * (min(lane, 29) % 10);
                float cs[8] = {0.f, 0.f, 0.f, 0.f, 0.f, 0.f, 0.f, 0.f};
#pragma unroll 1
                for (int i0 = 0; i0 < 14; i0 += 7) {
                    uint4 v[7];
#pragma unroll
                    for (int i = 0; i < 7; i++) v[i] = (3 * (i0 + i) + hw < 40) ? __ldg((const uint4*)(wsrc + (size_t)(3 * (i0 + i)) * (3 * DM))) : make_uint4(0, 0, 0, 0);
#pragma unroll
                    for (int i = 0; i < 7; i++)
#pragma unroll
                        for (int j = 0; j < 4; j++) { cs[2 * j] += bf_lo(u4(v[i], j)); cs[2 * j + 1] += bf_hi(u4(v[i], j)); }
                }
                const uint32_t pa = sb + Q_EOFF + 8192;
                if (lane < 30) {
                    sts128(pa + (hw * 240 + 8 * lane) * 4, make_uint4(__float_as_uint(cs[0]), __float_as_uint(cs[1]), __float_as_uint(cs[2]), __float_as_uint(cs[3])));
                    sts128(pa + (hw * 240 + 8 * lane + 4) * 4, make_uint4(__float_as_uint(cs[4]), __float_as_uint(cs[5]), __float_as_uint(cs[6]), __float_as_uint(cs[7])));
                }
                named_bar(4, 96);
                if (ht < 80) {
                    float t[3];
#pragma unroll
                    for (int j = 0; j < 3; j++) t[j] = F(lds32(pa + (3 * ht + j) * 4)) + F(lds32(pa + (240 + 3 * ht + j) * 4)) + F(lds32(pa + (480 + 3 * ht + j) * 4));
                    st_ll4(&g_csp[hg][blk][ht], __float_as_uint(t[0]), __float_as_uint(t[1]), __float_as_uint(t[2]), tag);
                }
                if (ht == 0) TSX(2, 3);
#pragma unroll 1
                for (int i = ht >> 4; i < 18; i += 6) {
                    const bf16* src = xin + (size_t)(2 * ((srow & 1023) + min(i, 15)) + (hg >> 2)) * DM + 8 * (lane & 15);
                    uint4 v[5];
#pragma unroll
                    for (int j = 0; j < 5; j++) v[j] = __ldg((const uint4*)(src + 128 * j));
                    float a = 0.f, b = 0.f;
#pragma unroll
                    for (int j = 0; j < 5; j++)
#pragma unroll
                        for (int k = 0; k < 4; k++) {
                            const float lo = bf_lo(u4(v[j], k)), hi = bf_hi(u4(v[j], k));
                            a += lo + hi; b = fmaf(lo, lo, fmaf(hi, hi, b));
                        }
#pragma unroll
                    for (int o = 1; o <= 8; o <<= 1) { a += __shfl_xor_sync(~0u, a, o); b += __shfl_xor_sync(~0u, b, o); }
                    if ((lane & 15) == 0 && i < 16) { s_red[0][i] = a; s_red[0][16 + i] = b; }
                }
                if (hw) s_red[hw][lane] = 0.f;
            } else {
                float a[16];
#pragma unroll
                for (int j = 0; j < 16; j++) a[j] = 0.f;
                const bf16* src = xin + (size_t)(ht >> 1) * XP + srow + 8 * (lane & 1);
#pragma unroll 1
                for (int i0 = 0; i0 < 14; i0 += 7) {
                    uint4 v[7];
#pragma unroll
                    for (int i = 0; i < 7; i++) {
                        v[i] = make_uint4(0, 0, 0, 0);
                        if (48 * (i0 + i) + (ht >> 1) < DM) v[i] = ldg128(src + (size_t)48 * (i0 + i) * XP);
                    }
#pragma unroll
                    for (int i = 0; i < 7; i++)
#pragma unroll
                        for (int j = 0; j < 4; j++) {
                            const float lo = bf_lo(u4(v[i], j)), hi = bf_hi(u4(v[i], j));
                            a[2 * j] += lo; a[8 + 2 * j] = fmaf(lo, lo, a[8 + 2 * j]); a[2 * j + 1] += hi; a[9 + 2 * j] = fmaf(hi, hi, a[9 + 2 * j]);
                        }
                }
#pragma unroll
                for (int l = 0; l < 4; l++) {
                    const int n = 8 >> l;
                    const bool up = lane & (2 * n);
#pragma unroll
                    for (int j = 0; j < 8; j++)
                        if (j < n) { const float lo = a[j], hi = a[j + n]; a[j] = (up ? hi : lo) + __shfl_xor_sync(~0u, up ? lo : hi, 2 * n); }
                }
                s_red[hw][(lane & 16) + 8 * (lane & 1) + ((lane >> 1) & 7)] = a[0];
            }
#pragma unroll 1
            for (int i = ht; i < 1280; i += 96) stg128(&g_of[blk][hg][0][0][0] + i, make_uint4(0, 0, 0, 0));
            if (ht < 32) sums[(ht >> 4) * SEQ + srow + (ht & 15)] = 0.f;
            asm volatile("fence.release.gpu;" ::: "memory");
            named_bar(4, 96);
            if (ht < 16) st_ll(g_stats + srow + ht, ln_finish_packed(s_red[0][ht] + s_red[1][ht] + s_red[2][ht], s_red[0][16 + ht] + s_red[1][16 + ht] + s_red[2][16 + ht]), tag);
            if (ht == 0) TSX(2, 4);
            if (ht < 80) {
                float t[3] = {0.f, 0.f, 0.f};
                int ci[3];
#pragma unroll
                for (int j = 0; j < 3; j++) ci[j] = ((3 * ht + j) / 80) * DM + hg * 80 + (3 * ht + j) % 80;
                if (layer == 0) {
#pragma unroll 1
                    for (int j0 = 0; j0 < 16; j0 += 8) {
                        uint4 v[8];
                        int spin = 0;
                        bool ok;
                        do {
                            ok = true;
#pragma unroll
                            for (int j = 0; j < 8; j++) v[j] = ld_ll4(&g_csp[hg][j0 + j][ht]);
#pragma unroll
                            for (int j = 0; j < 8; j++) ok = ok && v[j].w == tag;
                        } while (!ok && ++spin < (1 << 18));
#pragma unroll
                        for (int j = 0; j < 8; j++) { t[0] += F(v[j].x); t[1] += F(v[j].y); t[2] += F(v[j].z); }
                    }
                    if (blk == 0) { g_colsum[ci[0]] = t[0]; g_colsum[ci[1]] = t[1]; g_colsum[ci[2]] = t[2]; }
                } else {
#pragma unroll
                    for (int j = 0; j < 3; j++) t[j] = F(ldg32(g_colsum + ci[j]));
                }
#pragma unroll
                for (int j = 0; j < 3; j++) s_cs[3 * ht + j] = t[j];
            }
            if (ht < 72) {
                const unsigned long long* sp0 = g_stats + 64 * blk + ((blk || ht >= 8) ? ht - 8 : 0);
                unsigned long long v0, v1;
                int spin = 0;
                do { v0 = ld_ll(sp0); v1 = ld_ll(sp0 + 1024); } while (((uint32_t)(v0 >> 32) != tag || (uint32_t)(v1 >> 32) != tag) && ++spin < (1 << 18));
                s_mean[0][ht] = bf_hi((uint32_t)v0); s_rstd[0][ht] = frcp(bf_lo((uint32_t)v0));
                s_mean[1][ht] = bf_hi((uint32_t)v1); s_rstd[1][ht] = frcp(bf_lo((uint32_t)v1));
            }
            asm volatile("fence.acquire.gpu;" ::: "memory");
            mbar_arrive(s2u(&s_prep));
            if (ht == 0) TSX(2, 5);
            if (layer == 0) {
                __syncwarp();
                cluster_wait();
                named_bar(8, 384);
                kgen_expand(blockIdx.x * 5, sb + Q_KDUMP, &s_kg, ht, sp TS_PASS);
                asm volatile("fence.release.gpu;" ::: "memory");
                named_bar(4, 96);
                pdl_launch();
                if (ht == 0) TSX(2, 7);
            }
        }
        TS_END(slot);
    } else {
    asm volatile("setmaxnreg.inc.sync.aligned.u32 216;");
    const int wg = warp >> 2, w = warp & 3;
    const int mi = lane >> 3, mj = lane & 7;
    TS(2);
    float acc[120];
    auto release = [&](int it) {
        if (lane == 0) { mbar_arrive_cta(s2u(&s_empty[it & (Q_ST - 1)]), 0); mbar_arrive_cta(s2u(&s_empty[it & (Q_ST - 1)]), 1); }
    };
#pragma unroll 1
    for (int it = 0; it < 10; it++) {
        const int s = it & (Q_ST - 1);
        const uint32_t st = sb + s * Q_SB;
        const bool hold = wg == 1 && it == Q_S0;
        if (hold) {
            wg_wait<0>();
            release(it - 1);
            mbar_wait(s2u(&s_go), 0);
        }
        mbar_wait(s2u(&s_full[s]), (it >> 2) & 1);
        if (it < 2) TS(3 + it);
        if (it == 6) TS(5);
        if (it == 9) TS(6);
        const uint64_t da = mkdesc(st + wg * 8192, 16, 1024, 1);
        const uint64_t db = mkdesc(st + Q_AB, 4096, 1024, 1);
        const uint64_t dr = mkdesc(st + Q_AB + 12288, 1024, 256, 3);
        wg_fence();
        if (layer == 0) {
#pragma unroll
            for (int ks = 0; ks < 4; ks++) {
                const int sc = (ks > 0) ? 1 : (it > 0);
                wgmma_n192<0, 1>(*(float(*)[96]) & acc[0], da + ks * 2, db + (ks >> 1) * 960 + (ks & 1) * 128, sc);
                wgmma_n48<0, 1>(*(float(*)[24]) & acc[96], da + ks * 2, dr + (ks >> 1) * 960 + (ks & 1) * 32, sc);
            }
            wg_commit();
        } else {
#pragma unroll
            for (int ks = 0; ks < 4; ks++) {
                const int sc = (ks > 0) ? 1 : (it > 0);
                wgmma_n192<1, 1>(*(float(*)[96]) & acc[0], da + ks * 128, db + (ks >> 1) * 960 + (ks & 1) * 128, sc);
                wgmma_n48<1, 1>(*(float(*)[24]) & acc[96], da + ks * 128, dr + (ks >> 1) * 960 + (ks & 1) * 32, sc);
            }
            wg_commit();
        }
        wg_wait<1>();
        if (it > 0 && !hold) release(it - 1);
    }
    if (wg == 0 && lane == 0) mbar_arrive(s2u(&s_go));
    const uint32_t tag = 2u * ldg32(&g_epoch) + layer + 1u;
    if (layer == 0) cluster_wait();
    mbar_wait(s2u(&s_prep), 0);
    const bool first = (blk == 0 && w == 0);
    const bool sel0 = (2 * q > g), sel1 = (2 * q + 1 > g);
    constexpr float SC = 0.22360679774997896f * 1.4426950408889634f;
    const float m0 = s_mean[wg][8 + 16 * w + g], m1 = s_mean[wg][16 + 16 * w + g];
    const float* rs = &s_rstd[wg][16 * w];
    const float kx0 = rs[2 * q + (sel0 ? 0 : 8)], kx1 = rs[2 * q + (sel1 ? 1 : 9)], ky0 = rs[2 * q + (sel0 ? 8 : 16)], ky1 = rs[2 * q + (sel1 ? 9 : 17)];
    const float cx0 = SC * rs[8 + g] * kx0, cx1 = SC * rs[8 + g] * kx1, cy0 = SC * rs[16 + g] * ky0, cy1 = SC * rs[16 + g] * ky1;
    wg_wait<0>();
    TS(7);
    if (lane == 0) mbar_arrive(s2u(&s_qdone));
    uint32_t ql[10], qh[10], kl[10], kh[10], vl[10], vh[10];
    auto fold = [&](int p, int f, uint32_t& lo, uint32_t& hi) {
        const int j = (f < 8) ? 8 * p + f : 24 + 2 * p + (f - 8);
        const float2 c = *(const float2*)&s_cs[p * 80 + 8 * f + 2 * q];
        lo = pack2(fmaf(-m0, c.x, acc[4 * j]), fmaf(-m0, c.y, acc[4 * j + 1]));
        hi = pack2(fmaf(-m1, c.x, acc[4 * j + 2]), fmaf(-m1, c.y, acc[4 * j + 3]));
    };
#pragma unroll
    for (int f = 0; f < 10; f++) { fold(1, f, kl[f], kh[f]); fold(2, f, vl[f], vh[f]); }
    if (w == 3) {
        uint4* hp = &g_halo[blockIdx.x][wg][0][lane];
        st_ll4(hp, kh[0], kh[1], kh[2], tag); st_ll4(hp + 32, kh[3], kh[4], kh[5], tag); st_ll4(hp + 64, kh[6], kh[7], kh[8], tag);
        st_ll4(hp + 96, kh[9], vh[0], vh[1], tag); st_ll4(hp + 128, vh[2], vh[3], vh[4], tag); st_ll4(hp + 160, vh[5], vh[6], vh[7], tag);
        st_ll4(hp + 192, vh[8], vh[9], 0u, tag);
    } else {
        const uint32_t a = sb + Q_EOFF + warp * Q_ESLOT + mj * Q_EROW + mi * 16;
        stsm_x4(a, kh[0], kh[1], kh[2], kh[3]);
        stsm_x4(a + 64, kh[4], kh[5], kh[6], kh[7]);
        stsm_x4(a + 128, kh[8], kh[9], vh[0], vh[1]);
        stsm_x4(a + 192, vh[2], vh[3], vh[4], vh[5]);
        stsm_x4(a + 256, vh[6], vh[7], vh[8], vh[9]);
        __syncwarp();
        if (lane == 0) mbar_arrive(s2u(&s_ex[warp]));
    }
    TS(9);
#pragma unroll
    for (int f = 0; f < 10; f++) fold(0, f, ql[f], qh[f]);
    uint32_t vt1[10], vt2[10];
#pragma unroll
    for (int f = 0; f < 10; f++) { vt1[f] = movm_t(vl[f]); vt2[f] = movm_t(vh[f]); }
    TS(10);
    uint32_t kp[10], vp[10];
    if (w > 0) {
        const uint32_t a = sb + Q_EOFF + (warp - 1) * Q_ESLOT + mj * Q_EROW + mi * 16;
        mbar_wait(s2u(&s_ex[warp - 1]), 0);
        ldsm_x4(kp[0], kp[1], kp[2], kp[3], a);
        ldsm_x4(kp[4], kp[5], kp[6], kp[7], a + 64);
        ldsm_x2(kp[8], kp[9], a + 128);
        ldsm_x4_t(vp[0], vp[1], vp[2], vp[3], a + 160);
        ldsm_x4_t(vp[4], vp[5], vp[6], vp[7], a + 224);
        ldsm_x2_t(vp[8], vp[9], a + 288 - (lane >> 4) * 32);
    } else if (blk > 0) {
        const uint4* hp = &g_halo[blockIdx.x - 1][wg][0][lane];
        uint4 hv[7];
        int spin = 0;
        bool ok;
        do {
            ok = true;
#pragma unroll
            for (int f = 0; f < 7; f++) hv[f] = ld_ll4(hp + 32 * f);
#pragma unroll
            for (int f = 0; f < 7; f++) ok = ok && hv[f].w == tag;
        } while (!__all_sync(~0u, ok) && ++spin < (1 << 18));
#pragma unroll
        for (int f = 0; f < 10; f++) { kp[f] = u4(hv[f / 3], f % 3); vp[f] = movm_t(u4(hv[(10 + f) / 3], (10 + f) % 3)); }
    } else {
#pragma unroll
        for (int f = 0; f < 10; f++) { kp[f] = 0u; vp[f] = 0u; }
    }
    TS(12);
    float oacc[10][4];
#pragma unroll
    for (int h = 0; h < 4; h++) {
        const int fa = (h == 0) ? 0 : (h == 1) ? 3 : (h == 2) ? 5 : 8, fb = fa + 1, fh = (h < 2) ? 2 : 7;
        const bool mine = (h & 1) ? (q >= 2) : (q < 2);
        const uint32_t qml = mine ? ql[fh] : 0u, qmh = mine ? qh[fh] : 0u;
        float S0[4] = {0.f, 0.f, 0.f, 0.f}, S1[4] = {0.f, 0.f, 0.f, 0.f}, S2[4] = {0.f, 0.f, 0.f, 0.f};
        mma16816(S0, ql[fa], qh[fa], ql[fb], qh[fb], kp[fa], kp[fb]); mma1688(S0, qml, qmh, kp[fh]);
        mma16816(S1, ql[fa], qh[fa], ql[fb], qh[fb], kl[fa], kl[fb]); mma1688(S1, qml, qmh, kl[fh]);
        mma16816(S2, ql[fa], qh[fa], ql[fb], qh[fb], kh[fa], kh[fb]); mma1688(S2, qml, qmh, kh[fh]);
        float x0 = (sel0 ? S0[0] : S1[0]) * cx0, x1 = (sel1 ? S0[1] : S1[1]) * cx1;
        float y0 = (sel0 ? S1[2] : S2[2]) * cy0, y1 = (sel1 ? S1[3] : S2[3]) * cy1;
        if (first) { if (sel0) x0 = -INFINITY; if (sel1) x1 = -INFINITY; }
        float mx = fmaxf(x0, x1), my = fmaxf(y0, y1);
        mx = fmaxf(mx, __shfl_xor_sync(~0u, mx, 1)); my = fmaxf(my, __shfl_xor_sync(~0u, my, 1));
        mx = fmaxf(mx, __shfl_xor_sync(~0u, mx, 2)); my = fmaxf(my, __shfl_xor_sync(~0u, my, 2));
        x0 = ex2(x0 - mx); x1 = ex2(x1 - mx); y0 = ex2(y0 - my); y1 = ex2(y1 - my);
        float sx = x0 + x1, sy = y0 + y1;
        sx += __shfl_xor_sync(~0u, sx, 1); sy += __shfl_xor_sync(~0u, sy, 1);
        sx += __shfl_xor_sync(~0u, sx, 2); sy += __shfl_xor_sync(~0u, sy, 2);
        const float ix = frcp(sx), iy = frcp(sy);
        x0 *= ix * kx0; x1 *= ix * kx1; y0 *= iy * ky0; y1 *= iy * ky1;
        const uint32_t pa0 = pack2(sel0 ? x0 : 0.f, sel1 ? x1 : 0.f);
        const uint32_t pa2 = pack2(sel0 ? 0.f : x0, sel1 ? 0.f : x1);
        const uint32_t pa3 = pack2(sel0 ? y0 : 0.f, sel1 ? y1 : 0.f);
        const uint32_t pb1 = pack2(sel0 ? 0.f : y0, sel1 ? 0.f : y1);
#pragma unroll
        for (int i = 0; i < 3; i++) {
            const int f = (i == 0) ? fa : (i == 1) ? fb : fh;
            float O[4] = {0.f, 0.f, 0.f, 0.f};
            mma16816(O, pa0, 0u, pa2, pa3, vp[f], vt1[f]);
            mma1688(O, 0u, pb1, vt2[f]);
            if (i < 2 || !(h & 1) || mine) { oacc[f][0] = O[0]; oacc[f][1] = O[1]; oacc[f][2] = O[2]; oacc[f][3] = O[3]; }
        }
    }
    TS(13);
    uint4 of[5][5];
    {
        uint4* dst = &g_of[blk][hg][warp][0][lane];
#pragma unroll
        for (int k = 0; k < 5; k++) {
            of[0][k] = make_uint4(pack2(oacc[2 * k][0], oacc[2 * k][1]), pack2(oacc[2 * k][2], oacc[2 * k][3]),
                                  pack2(oacc[2 * k + 1][0], oacc[2 * k + 1][1]), pack2(oacc[2 * k + 1][2], oacc[2 * k + 1][3]));
            st_ll4(dst + 32 * k, of[0][k].x ? of[0][k].x : 0x80000000u, of[0][k].y, of[0][k].z, of[0][k].w);
        }
    }
    if (Q_WGATE && wg == 1 && lane == 0) mbar_arrive(s2u(&s_att));
    TS(14);
    const uint4* osrc = &g_of[blk][0][warp][0][lane];
    auto oload = [&](int j) {
        const uint4* p = osrc + ((hg + j) & 7) * 1280;
#pragma unroll
        for (int k = 0; k < 5; k++) of[j % 5][k] = ld_ll4(p + 32 * k);
    };
    {
        const uint32_t* pp = &g_of[blk][(hg + 1 + (lane & 3)) & 7][warp][4][31].x;
        uint32_t v;
        int spin = 0;
        do { asm volatile("ld.relaxed.gpu.global.u32 %0, [%1];" : "=r"(v) : "l"(pp) : "memory"); } while (!__all_sync(~0u, v != 0u) && ++spin < (1 << 18));
    }
    TS(15);
#pragma unroll
    for (int j = 1; j < 5; j++) oload(j);
    float a64[32], a16[8];
    if (Q_WGATE && wg == 0) mbar_wait(s2u(&s_att), 0);
#pragma unroll
    for (int j = 0; j < 8; j++) {
        if (j == 0 || j == 2 || j == 4) mbar_wait(s2u(&s_wfull[j >> 1]), 0);
        if (j > 0) {
            int spin = 0;
            while (true) {
                bool ok = true;
#pragma unroll
                for (int k = 0; k < 5; k++) ok = ok && of[j % 5][k].x != 0u;
                if (__all_sync(~0u, ok) || ++spin >= (1 << 18)) break;
                oload(j);
            }
        }
        if (j == 0) TS(16);
        if (j == 1) TS(17);
        if (j == 5) TS(18);
        const uint64_t dm = mkdesc(sb + w_main(j), 4096, 1024, 1), dr = mkdesc(sb + w_rem(j), 1024, 256, 3);
        wg_fence();
#pragma unroll
        for (int k = 0; k < 5; k++) {
            wgmma_rs64(a64, of[j % 5][k], dm + k * 128, j + k > 0);
            wgmma_rs16(a16, of[j % 5][k], dr + k * 32, j + k > 0);
        }
        wg_commit();
        if (j >= 1 && j <= 3) { wg_wait<1>(); oload(j + 4); }
    }
    uint32_t res[20];
    mbar_wait(s2u(&s_res), 0);
    const uint32_t ta = (8 * (mi >> 1) + mj) * 128 + (((2 * w + (mi & 1)) ^ mj) << 4);
    if (layer == 0) {
        const int tok = 16 * w + 8 * (mi & 1) + mj;
#pragma unroll
        for (int k = 0; k < 4; k++)
            ldsm_x4(res[4 * k], res[4 * k + 1], res[4 * k + 2], res[4 * k + 3], sb + W_RES + wg * 8192 + tok * 128 + (((2 * k + (mi >> 1)) ^ mj) << 4));
        ldsm_x4(res[16], res[17], res[18], res[19], sb + W_RES + 16384 + wg * 2048 + tok * 32 + (((mi >> 1) ^ (mj >> 2)) << 4));
    } else {
#pragma unroll
        for (int k = 0; k < 5; k++) ldsm_x4_t(res[4 * k], res[4 * k + 1], res[4 * k + 2], res[4 * k + 3], sb + W_RES + wg * 10240 + k * 2048 + ta);
    }
    mbar_wait(s2u(&s_qdone), 0);
    wg_wait<0>();
    TS(19);
#pragma unroll
    for (int i = 0; i < 20; i++) {
        const uint32_t y = i < 16 ? pack2(a64[2 * i], a64[2 * i + 1]) : pack2(a16[2 * i - 32], a16[2 * i - 31]);
        asm("add.rn.bf16x2 %0, %0, %1;" : "+r"(res[i]) : "r"(y));
    }
#pragma unroll
    for (int k = 0; k < 5; k++) stsm_x4_t(sb + W_OUT + wg * 10240 + k * 2048 + ta, res[4 * k], res[4 * k + 1], res[4 * k + 2], res[4 * k + 3]);
    fence_async_smem();
    named_bar(1 + wg, 128);
    if ((tid & 127) == 0) {
        asm volatile("cp.async.bulk.tensor.2d.global.shared::cta.bulk_group [%0, {%2, %3}], [%1];"
                     ::"l"(&mOut), "r"(sb + W_OUT + wg * 10240), "r"(1024 * wg + 64 * blk), "r"(hg * 80) : "memory");
        asm volatile("cp.async.bulk.commit_group;" ::: "memory");
    }
    TS(20);
    {
        float sm[4] = {0.f, 0.f, 0.f, 0.f}, d0[4] = {0.f, 0.f, 0.f, 0.f}, d1[4] = {0.f, 0.f, 0.f, 0.f};
#pragma unroll
        for (int k = 0; k < 5; k++) {
            mma16816(sm, res[4 * k], res[4 * k + 1], res[4 * k + 2], res[4 * k + 3], 0x3F803F80u, 0x3F803F80u);
            mma16816(d0, res[4 * k], res[4 * k + 1], res[4 * k + 2], res[4 * k + 3], res[4 * k], res[4 * k + 2]);
            mma16816(d1, res[4 * k], res[4 * k + 1], res[4 * k + 2], res[4 * k + 3], res[4 * k + 1], res[4 * k + 3]);
        }
        const bool diag = q == (g >> 1);
        if (diag || q == ((g >> 1) ^ 1)) {
            float* dst = sums + (diag ? SEQ : 0) + 1024 * wg + 64 * blk + 16 * w + g;
            asm volatile("red.global.add.f32 [%0], %1;" ::"l"(dst), "f"(diag ? ((g & 1) ? d0[1] : d0[0]) : sm[0]) : "memory");
            asm volatile("red.global.add.f32 [%0], %1;" ::"l"(dst + 8), "f"(diag ? ((g & 1) ? d1[3] : d1[2]) : sm[2]) : "memory");
        }
    }
    TS(21);
    if ((tid & 127) == 0) asm volatile("cp.async.bulk.wait_group 0;" ::: "memory");
    TS_END(slot);
    }
}
__device__ __forceinline__ void wgmma_h64_rs(uint32_t (&d)[16], const uint4& a, uint64_t db, int scale_d) {
    asm volatile("{\n.reg .pred p;\nsetp.ne.b32 p, %21, 0;\n"
                 "wgmma.mma_async.sync.aligned.m64n64k16.f16.f16.f16 {%0,%1,%2,%3,%4,%5,%6,%7,%8,%9,%10,%11,%12,%13,%14,%15}, {%16,%17,%18,%19}, %20, p, 1, 1, 1;\n}\n"
                 : "+r"(d[0]), "+r"(d[1]), "+r"(d[2]), "+r"(d[3]), "+r"(d[4]), "+r"(d[5]), "+r"(d[6]), "+r"(d[7]), "+r"(d[8]), "+r"(d[9]),
                   "+r"(d[10]), "+r"(d[11]), "+r"(d[12]), "+r"(d[13]), "+r"(d[14]), "+r"(d[15])
                 : "r"(a.x), "r"(a.y), "r"(a.z), "r"(a.w), "l"(db), "r"(scale_d));
}
__device__ __forceinline__ void wgmma_h32_rs(uint32_t (&d)[8], const uint32_t (&a)[4], uint64_t db, int scale_d) {
    asm volatile("{\n.reg .pred p;\nsetp.ne.b32 p, %13, 0;\n"
                 "wgmma.mma_async.sync.aligned.m64n32k16.f16.f16.f16 {%0,%1,%2,%3,%4,%5,%6,%7}, {%8,%9,%10,%11}, %12, p, 1, 1, 0;\n}\n"
                 : "+r"(d[0]), "+r"(d[1]), "+r"(d[2]), "+r"(d[3]), "+r"(d[4]), "+r"(d[5]), "+r"(d[6]), "+r"(d[7])
                 : "r"(a[0]), "r"(a[1]), "r"(a[2]), "r"(a[3]), "l"(db), "r"(scale_d));
}
__device__ __forceinline__ void wgmma_sp64_rs(float (&d)[32], const uint4& a, uint64_t db, uint32_t meta, int scale_d) {
    asm volatile("{\n.reg .pred p;\nsetp.ne.b32 p, %38, 0;\n"
                 "wgmma.mma_async.sp.sync.aligned.m64n64k32.f32.f16.f16 "
                 "{%0,%1,%2,%3,%4,%5,%6,%7,%8,%9,%10,%11,%12,%13,%14,%15,%16,%17,%18,%19,%20,%21,%22,%23,%24,%25,%26,%27,%28,%29,%30,%31}, "
                 "{%32,%33,%34,%35}, %36, %37, 0, p, 1, 1, 1;\n}\n"
                 : "+f"(d[0]), "+f"(d[1]), "+f"(d[2]), "+f"(d[3]), "+f"(d[4]), "+f"(d[5]), "+f"(d[6]), "+f"(d[7]), "+f"(d[8]), "+f"(d[9]),
                   "+f"(d[10]), "+f"(d[11]), "+f"(d[12]), "+f"(d[13]), "+f"(d[14]), "+f"(d[15]), "+f"(d[16]), "+f"(d[17]), "+f"(d[18]), "+f"(d[19]),
                   "+f"(d[20]), "+f"(d[21]), "+f"(d[22]), "+f"(d[23]), "+f"(d[24]), "+f"(d[25]), "+f"(d[26]), "+f"(d[27]), "+f"(d[28]), "+f"(d[29]),
                   "+f"(d[30]), "+f"(d[31])
                 : "r"(a.x), "r"(a.y), "r"(a.z), "r"(a.w), "l"(db), "r"(meta), "r"(scale_d));
}

#define F_KFIRST 1
constexpr int F_S23 = 0;
constexpr int F_WG = 8192, F_WGB = 24576;
constexpr int F_SMEM = F_WG + 3 * F_WGB + 1024;

__device__ __forceinline__ void fft_stage(const uint32_t (&u)[2][2][4], uint32_t eo, int warp4, int lane) {
    const int mi = lane >> 3, mj = lane & 7;
#pragma unroll
    for (int c = 0; c < 2; c++) {
        const uint32_t a = eo + (8 * warp4 + mj) * 128 + (((4 * c + mi) ^ mj) << 4);
        stsm_x4(a, hadd(u[c][0][0], u[c][1][0]), hadd(u[c][0][1], u[c][1][1]), hadd(u[c][0][2], u[c][1][2]), hadd(u[c][0][3], u[c][1][3]));
        stsm_x4(a + 4096, hsub(u[c][0][0], u[c][1][0]), hsub(u[c][0][1], u[c][1][1]), hsub(u[c][0][2], u[c][1][2]), hsub(u[c][0][3], u[c][1][3]));
    }
    fence_async_smem();
}
__device__ __forceinline__ void fft_forward(const uint4 (&a1)[4], const uint4 (&tw)[4], uint32_t eo, uint32_t s2, uint32_t (&X)[2][2][8]) {
    uint32_t dr[16], di[16];
    const uint64_t de = mkdesc(eo, 4096, 1024, 1), d2 = mkdesc(s2, 16, 1024, 1);
    wg_fence();
    wgmma_h64_rs(dr, a1[0], de, 0);
    wgmma_h64_rs(di, a1[2], de + 256, 0);
    wgmma_h64_rs(dr, a1[1], de + 128, 1);
    wgmma_h64_rs(di, a1[3], de + 384, 1);
    wg_commit();
    wg_wait<0>();
#pragma unroll
    for (int c = 0; c < 2; c++) {
        uint32_t zr[2][4], zi[2][4];
#pragma unroll
        for (int p = 0; p < 2; p++)
#pragma unroll
            for (int i = 0; i < 4; i++) {
                const uint32_t r = dr[8 * c + 4 * p + i], m = di[8 * c + 4 * p + i], tr = u4(tw[p], i), ti = u4(tw[2 + p], i);
                zr[p][i] = hfms(m, ti, hmul(r, tr));
                zi[p][i] = hfma(m, tr, hmul(r, ti));
            }
        wg_fence();
        wgmma_h32_rs(X[c][0], zr[0], d2, 0);
        wgmma_h32_rs(X[c][1], zr[1], d2 + 4, 0);
        wgmma_h32_rs(X[c][0], zi[0], d2 + 2, 1);
        wgmma_h32_rs(X[c][1], zi[1], d2 + 6, 1);
        wg_commit();
    }
}

__global__ void __launch_bounds__(384, 1) conv_kernel(const bf16* xT, const float* sums, bf16* out, int slot) {
    extern __shared__ __align__(1024) char smraw[];
    __shared__ __align__(8) uint64_t kbar;
    const uint32_t sb = (s2u(smraw) + 1023) & ~1023u;
    const int tid = threadIdx.x, warp = __shfl_sync(~0u, tid >> 5, 0), lane = tid & 31;
    const int wg = warp >> 2, w = warp & 3, t = tid & 127, g = lane >> 2, q = lane & 3, mi = lane >> 3, mj = lane & 7;
    const int npair = min(3, DM / 2 - 3 * (int)blockIdx.x), ch0 = 6 * blockIdx.x + 2 * wg;
    const uint32_t wb = sb + F_WG + wg * F_WGB;
    TS_DECL;
    TS_BEGIN;
    if (tid == 0) {
        mbar_init(s2u(&kbar), 1);
        fence_mbar_init();
        mbar_expect(s2u(&kbar), 8192 + npair * 8192);
#pragma unroll 1
        for (int i = 0; i < npair; i++) bulk_g2s(sb + F_WG + i * F_WGB + 8192, g_keo[3 * blockIdx.x + i], 8192, s2u(&kbar));
        bulk_g2s(sb + F_S23, c_fft + 18 * 512, 8192, s2u(&kbar));
    }
    uint4 a1[4], tw[4];
#pragma unroll
    for (int i = 0; i < 4; i++) { a1[i] = ldg_tab(i, t); tw[i] = ldg_tab(8 + i, t); }
    __syncthreads();
    pdl_launch();
    if (wg >= npair) return;
    uint32_t u[2][2][4], KH[2][2][8];
    const uint2 ke = ldg64(g_ksc + ch0);
    const uint32_t oscale[2] = {(ke.x + 3u) * 0x00800080u, (ke.y + 3u) * 0x00800080u};
    TS(1);
    mbar_wait(s2u(&kbar), 0);
    TS(2);
    fft_forward(a1, tw, wb + 8192, sb + F_S23, KH);
#pragma unroll
    for (int i = 0; i < 4; i++) tw[i] = ldg_tab(4 + i, t);
    TS(4);
    pdl_wait();
    TS(5);
    uint2 x[2][2][2];
    const int ra[2] = {16 * (8 * w + g) + 4 * q, 16 * (63 - 8 * w - g) + 4 * q};
    {
        uint4 s[2][2][2];
#pragma unroll
        for (int h = 0; h < 2; h++)
#pragma unroll
            for (int p = 0; p < 2; p++) {
                s[h][p][0] = ldg128(sums + 1024 * p + ra[h]);
                s[h][p][1] = ldg128(sums + SEQ + 1024 * p + ra[h]);
#pragma unroll
                for (int c = 0; c < 2; c++) x[c][h][p] = ldg64(xT + (size_t)(ch0 + c) * XP + 1024 * p + ra[h]);
            }
        TS(6);
        TS(7);
#pragma unroll
        for (int h = 0; h < 2; h++)
#pragma unroll
            for (int j = 0; j < 4; j++) {
                const uint4 sa = s[h][j >> 1][0], sq = s[h][j >> 1][1];
                const float4 v = make_float4(__uint_as_float(u4(sa, 2 * (j & 1))), __uint_as_float(u4(sq, 2 * (j & 1))),
                                             __uint_as_float(u4(sa, 2 * (j & 1) + 1)), __uint_as_float(u4(sq, 2 * (j & 1) + 1)));
                const float m0 = v.x * (1.0f / DM), m1 = v.z * (1.0f / DM);
                const float r0 = frsq(fmaxf(fmaf(v.y, 1.0f / DM, fmaf(-m0, m0, 1e-5f)), 1e-5f));
                const float r1 = frsq(fmaxf(fmaf(v.w, 1.0f / DM, fmaf(-m1, m1, 1e-5f)), 1e-5f));
                const float c0 = -m0 * r0, c1 = -m1 * r1;
#pragma unroll
                for (int c = 0; c < 2; c++) {
                    const uint32_t xv = (j & 1) ? x[c][h][j >> 1].y : x[c][h][j >> 1].x;
                    u[c][h][j] = pack2h(fmaf(bf_lo(xv), r0, c0), fmaf(bf_hi(xv), r1, c1));
                }
            }
    }
    TS(8);
    uint32_t X[2][2][8], Y[2][2][8];
    fft_stage(u, wb, w, lane);
    wg_wait<0>();
    TS(9);
    named_bar(1 + wg, 128);
    fft_forward(a1, tw, wb, sb + F_S23, X);
    TS(10);
#pragma unroll
    for (int i = 0; i < 4; i++) a1[i] = ldg_tab(12 + i, t);
    const uint64_t d3 = mkdesc(sb + F_S23 + 4096, 16, 1024, 1);
#pragma unroll
    for (int c = 0; c < 2; c++) {
        wg_wait<1>();
        TS(11 + c);
        uint32_t pr[2][4], pi[2][4];
#pragma unroll
        for (int i = 0; i < 4; i++) {
            const uint32_t er = X[c][0][i], ei = X[c][0][4 + i], orr = X[c][1][i], oi = X[c][1][4 + i];
            const uint32_t ar = KH[c][0][i], ai = KH[c][0][4 + i], br = KH[c][1][i], bi = KH[c][1][4 + i];
            pr[0][i] = hfms(bi, oi, hfma(br, orr, hfms(ai, ei, hmul(ar, er))));
            pi[0][i] = hfma(bi, orr, hfma(br, oi, hfma(ai, er, hmul(ar, ei))));
            pr[1][i] = hfms(ai, oi, hfma(ar, orr, hfms(bi, ei, hmul(br, er))));
            pi[1][i] = hfma(ai, orr, hfma(ar, oi, hfma(bi, er, hmul(br, ei))));
        }
        wg_fence();
        wgmma_h32_rs(Y[c][0], pr[0], d3, 0);
        wgmma_h32_rs(Y[c][1], pr[1], d3 + 4, 0);
        wgmma_h32_rs(Y[c][0], pi[0], d3 + 2, 1);
        wgmma_h32_rs(Y[c][1], pi[1], d3 + 6, 1);
        wg_commit();
    }
    const uint32_t zb = wb + 8192;
#pragma unroll
    for (int c = 0; c < 2; c++) {
        if (c == 0) wg_wait<1>(); else wg_wait<0>();
        TS(13 + c);
        uint32_t zr[2][4], zi[2][4];
#pragma unroll
        for (int p = 0; p < 2; p++)
#pragma unroll
            for (int i = 0; i < 4; i++) {
                const uint32_t r = Y[c][p][i], m = Y[c][p][4 + i], tr = u4(tw[p], i), ti = u4(tw[2 + p], i);
                zr[i & 1][2 * p + (i >> 1)] = hfma(m, ti, hmul(r, tr));
                zi[i & 1][2 * p + (i >> 1)] = hfms(r, ti, hmul(m, tr));
            }
        const int kr = 4 * (mj >> 1) + (mj & 1) + 2 * (mj >> 2), ki = kr ^ 2;
#pragma unroll
        for (int h = 0; h < 2; h++) {
            const uint32_t a = zb + (2 * w + h) * 2048;
            stsm_x4(a + kr * 128 + (((4 * c + mi) ^ (kr & 7)) << 4), zr[h][0], zr[h][1], zr[h][2], zr[h][3]);
            stsm_x4(a + ki * 128 + (((4 * c + mi) ^ (ki & 7)) << 4), zi[h][0], zi[h][1], zi[h][2], zi[h][3]);
        }
    }
    TS(15);
    fence_async_smem();
    TS(16);
    named_bar(1 + wg, 128);
    TS(17);
    float acc[32];
    const uint64_t dz = mkdesc(zb, 4096, 1024, 1);
    wg_fence();
#pragma unroll
    for (int ks = 0; ks < 4; ks++) wgmma_sp64_rs(acc, a1[ks], dz + ks * 256, 0x44EEEE44u, ks > 0);
    wg_commit();
    wg_wait<0>();
    TS(18);
#pragma unroll
    for (int c = 0; c < 2; c++)
#pragma unroll
        for (int p = 0; p < 2; p++) {
            uint32_t r[2][2];
#pragma unroll
            for (int j = 0; j < 2; j++) {
                const float* d = acc + 4 * (4 * c + 2 * p + j);
                const uint32_t y0 = pack2(d[0] + d[2], d[1] + d[3]), y1 = pack2(d[0] - d[2], d[1] - d[3]);
                asm("fma.rn.bf16x2 %0, %1, %2, %3;" : "=r"(r[0][j]) : "r"(y0), "r"(oscale[c]), "r"(j ? x[c][0][p].y : x[c][0][p].x));
                asm("fma.rn.bf16x2 %0, %1, %2, %3;" : "=r"(r[1][j]) : "r"(y1), "r"(oscale[c]), "r"(j ? x[c][1][p].y : x[c][1][p].x));
            }
#pragma unroll
            for (int h = 0; h < 2; h++) *(uint2*)(out + (size_t)(ch0 + c) * XP + 1024 * p + ra[h]) = make_uint2(r[h][0], r[h][1]);
        }
    TS_END(slot);
}

constexpr int OT_SMEM = 120 * 1024;
__global__ void __launch_bounds__(256, 1) out_kernel(const bf16* __restrict__ xT, bf16* __restrict__ out, int slot) {
    constexpr int PITCH = 160 + 8;
    extern __shared__ __align__(1024) char smraw[];
    uint16_t* tile = (uint16_t*)smraw;
    const int tid = threadIdx.x, t0 = (blockIdx.x >> 2) * 64, c0 = (blockIdx.x & 3) * 160;
    TS_DECL;
    TS_BEGIN;
    pdl_wait();
    TS(1);
    uint4 v[5];
#pragma unroll
    for (int i = 0; i < 5; i++) {
        const int id = tid + 256 * i, c = id >> 3, p = (id >> 2) & 1, k = id & 3;
        v[i] = ldg128(xT + (size_t)(c0 + c) * XP + p * 1024 + (t0 >> 1) + 8 * k);
    }
#pragma unroll
    for (int i = 0; i < 5; i++) {
        const int id = tid + 256 * i, c = id >> 3, p = (id >> 2) & 1, k = id & 3;
        uint16_t* t = tile + (16 * k + p) * PITCH + c;
        const uint32_t w[4] = {v[i].x, v[i].y, v[i].z, v[i].w};
#pragma unroll
        for (int j = 0; j < 4; j++) { t[(4 * j) * PITCH] = (uint16_t)w[j]; t[(4 * j + 2) * PITCH] = (uint16_t)(w[j] >> 16); }
    }
    TS(2);
    __syncthreads();
#pragma unroll
    for (int i = 0; i < 5; i++) {
        const int id = tid + 256 * i, r = id / 20, c = id - r * 20;
        stg128(out + (size_t)(t0 + r) * DM + c0 + c * 8, *(const uint4*)(tile + r * PITCH + c * 8));
    }
    if (blockIdx.x == 0 && tid == 0) g_epoch = g_epoch + 1;
    TS_END(slot);
}
typedef CUresult (*EncodeTiledFn)(CUtensorMap*, CUtensorMapDataType, cuuint32_t, void*, const cuuint64_t*, const cuuint64_t*, const cuuint32_t*,
                                  const cuuint32_t*, CUtensorMapInterleave, CUtensorMapSwizzle, CUtensorMapL2promotion, CUtensorMapFloatOOBfill);

static void make_map(EncodeTiledFn enc, CUtensorMap* m, const void* base, int rank, const cuuint64_t* dims, const cuuint64_t* strides,
                     const cuuint32_t* box, CUtensorMapSwizzle sw) {
    cuuint32_t es[3] = {1, 1, 1};
    enc(m, CU_TENSOR_MAP_DATA_TYPE_BFLOAT16, rank, (void*)base, dims, strides, box, es, CU_TENSOR_MAP_INTERLEAVE_NONE, sw,
        sw == CU_TENSOR_MAP_SWIZZLE_128B ? CU_TENSOR_MAP_L2_PROMOTION_L2_128B : CU_TENSOR_MAP_L2_PROMOTION_NONE, CU_TENSOR_MAP_FLOAT_OOB_FILL_NONE);
}

template <typename... KArgs, typename... Args>
static void launch(void (*kern)(KArgs...), int grid, int block, int smem, int cluster, bool pdl, Args... args) {
    cudaLaunchConfig_t cfg = {};
    cfg.gridDim = dim3(grid); cfg.blockDim = dim3(block); cfg.dynamicSmemBytes = smem; cfg.stream = cudaStreamPerThread;
    cudaLaunchAttribute at[2];
    int n = 0;
    if (cluster > 1) { at[n].id = cudaLaunchAttributeClusterDimension; at[n].val.clusterDim.x = cluster; at[n].val.clusterDim.y = 1; at[n].val.clusterDim.z = 1; n++; }
    if (pdl) { at[n].id = cudaLaunchAttributeProgrammaticStreamSerialization; at[n].val.programmaticStreamSerializationAllowed = 1; n++; }
    cfg.attrs = at; cfg.numAttrs = n;
    cudaLaunchKernelEx(&cfg, kern, KArgs(args)...);
}

struct HostState {
    bool ready = false;
    const void* key[4] = {nullptr, nullptr, nullptr, nullptr};
    CUtensorMap mX[2], mRes[2], mW, mWr, mWo, mWor, mOut;
    bf16 *x1T, *x2T;
    float* sums;
};

extern "C" void kernel_launch(void* const* d_in, const int* in_sizes, int n_in, void* d_out, int out_size) {
    const bf16* x = (const bf16*)d_in[0];
    const bf16* wqkv = (const bf16*)d_in[1];
    const bf16* wo = (const bf16*)d_in[2];
    const bf16* lar = (const bf16*)d_in[4];
    const bf16* aim = (const bf16*)d_in[5];
    const bf16* cre = (const bf16*)d_in[6];
    const bf16* cim = (const bf16*)d_in[7];
    const bf16* logdt = (const bf16*)d_in[8];
    const bf16* dskip = (const bf16*)d_in[9];
    static HostState hs;
    if (!hs.ready || hs.key[0] != wqkv || hs.key[1] != wo || hs.key[2] != x) {
        void* fn = nullptr;
        cudaDriverEntryPointQueryResult qr;
        cudaGetDriverEntryPoint("cuTensorMapEncodeTiled", &fn, cudaEnableDefault, &qr);
        EncodeTiledFn enc = (EncodeTiledFn)fn;
        cudaGetSymbolAddress((void**)&hs.x1T, g_x1T);
        cudaGetSymbolAddress((void**)&hs.x2T, g_x2T);
        cudaGetSymbolAddress((void**)&hs.sums, g_sums);
        {
            cuuint64_t d[3] = {DM, SEQ / 2, 2}, s[2] = {DM * 4, DM * 2};
            cuuint32_t b[3] = {64, 64, 2}, br[3] = {16, 64, 2};
            make_map(enc, &hs.mX[0], x, 3, d, s, b, CU_TENSOR_MAP_SWIZZLE_128B);
            make_map(enc, &hs.mRes[0], x, 3, d, s, br, CU_TENSOR_MAP_SWIZZLE_32B);
            cuuint64_t d2[3] = {SEQ / 2, DM, 2}, s2[2] = {XP * 2, SEQ};
            cuuint32_t b2[3] = {64, 80, 2};
            make_map(enc, &hs.mX[1], hs.x2T, 3, d2, s2, b, CU_TENSOR_MAP_SWIZZLE_128B);
            make_map(enc, &hs.mRes[1], hs.x2T, 3, d2, s2, b2, CU_TENSOR_MAP_SWIZZLE_128B);
            cuuint64_t d3[2] = {SEQ, DM};
            make_map(enc, &hs.mOut, hs.x1T, 2, d3, s2, b2, CU_TENSOR_MAP_SWIZZLE_128B);
        }
        { cuuint64_t d[2] = {3 * DM, DM}, s[1] = {3 * DM * 2}; cuuint32_t b[2] = {64, 32};
          make_map(enc, &hs.mW, wqkv, 2, d, s, b, CU_TENSOR_MAP_SWIZZLE_128B); }
        { cuuint64_t d[3] = {DM, DM, 3}, s[2] = {3 * DM * 2, DM * 2}; cuuint32_t b[3] = {16, 32, 3};
          make_map(enc, &hs.mWr, wqkv, 3, d, s, b, CU_TENSOR_MAP_SWIZZLE_32B); }
        { cuuint64_t d[2] = {DM, DM}, s[1] = {DM * 2}; cuuint32_t b[2] = {64, 40}, br[2] = {16, 40};
          make_map(enc, &hs.mWo, wo, 2, d, s, b, CU_TENSOR_MAP_SWIZZLE_128B);
          make_map(enc, &hs.mWor, wo, 2, d, s, br, CU_TENSOR_MAP_SWIZZLE_32B); }
        cudaFuncSetAttribute(attn_kernel, cudaFuncAttributeMaxDynamicSharedMemorySize, Q_SMEM);
        cudaFuncSetAttribute(conv_kernel, cudaFuncAttributeMaxDynamicSharedMemorySize, F_SMEM);
        cudaFuncSetAttribute(out_kernel, cudaFuncAttributeMaxDynamicSharedMemorySize, OT_SMEM);
        hs.key[0] = wqkv; hs.key[1] = wo; hs.key[2] = x;
        hs.ready = true;
    }
    const SsmParams sp = {lar, aim, cre, cim, logdt, dskip};
    for (int l = 0; l < 2; l++) {
        const bf16* xin = l ? hs.x2T : x;
        launch(attn_kernel, 128, 384, Q_SMEM, 2, l > 0, hs.mX[l], hs.mW, hs.mWr, hs.mWo, hs.mWor, hs.mRes[l], hs.mOut, xin, wqkv, wo, hs.sums, sp, l, 2 * l);
        launch(conv_kernel, 107, 384, F_SMEM, 1, true, (const bf16*)hs.x1T, (const float*)hs.sums, hs.x2T, 2 * l + 1);
    }
    launch(out_kernel, 128, 256, OT_SMEM, 1, true, (const bf16*)hs.x2T, (bf16*)d_out, 4);
}
```

```cpp
#include <cuda_runtime.h>
#include <cuda.h>
#include <cuda_bf16.h>
#include <cuda_fp16.h>
#include <stdint.h>

typedef __nv_bfloat16 bf16;

constexpr int SEQ = 2048;
constexpr int DM  = 640;
constexpr int XP  = SEQ + 64;
constexpr int NMODE = 192;

__device__ __forceinline__ uint32_t s2u(const void* p) { return (uint32_t)__cvta_generic_to_shared(p); }
__device__ __forceinline__ void mbar_init(uint32_t b, int c) { asm volatile("mbarrier.init.shared::cta.b64 [%0], %1;" ::"r"(b), "r"(c)); }
__device__ __forceinline__ void mbar_expect(uint32_t b, uint32_t bytes) { asm volatile("mbarrier.arrive.expect_tx.shared::cta.b64 _, [%0], %1;" ::"r"(b), "r"(bytes) : "memory"); }
__device__ __forceinline__ void mbar_arrive(uint32_t b) { asm volatile("mbarrier.arrive.shared::cta.b64 _, [%0];" ::"r"(b) : "memory"); }
__device__ __forceinline__ void mbar_arrive_cta(uint32_t b, uint32_t cta) {
    asm volatile("{\n.reg .b32 ra;\nmapa.shared::cluster.u32 ra, %0, %1;\nmbarrier.arrive.shared::cluster.b64 _, [ra];\n}" ::"r"(b), "r"(cta) : "memory");
}
__device__ __forceinline__ void mbar_wait(uint32_t b, uint32_t ph) {
    asm volatile("{\n.reg .pred p;\nW: mbarrier.try_wait.parity.shared::cta.b64 p, [%0], %1;\n@p bra D;\nbra W;\nD:\n}" ::"r"(b), "r"(ph) : "memory");
}
__device__ __forceinline__ void fence_mbar_init() { asm volatile("fence.mbarrier_init.release.cluster;" ::: "memory"); }
__device__ __forceinline__ void cluster_sync() { asm volatile("barrier.cluster.arrive.aligned;\nbarrier.cluster.wait.aligned;" ::: "memory"); }
__device__ __forceinline__ void pdl_wait() { asm volatile("griddepcontrol.wait;" ::: "memory"); }
__device__ __forceinline__ void pdl_launch() { asm volatile("griddepcontrol.launch_dependents;" ::: "memory"); }
__device__ __forceinline__ void named_bar(int id, int n) { asm volatile("bar.sync %0, %1;" ::"r"(id), "r"(n) : "memory"); }
__device__ __forceinline__ void fence_async_smem() { asm volatile("fence.proxy.async.shared::cta;" ::: "memory"); }

__device__ __forceinline__ void tma2d(uint32_t dst, const CUtensorMap* m, int c0, int c1, uint32_t bar) {
    asm volatile("cp.async.bulk.tensor.2d.shared::cluster.global.mbarrier::complete_tx::bytes [%0], [%1, {%3, %4}], [%2];"
                 ::"r"(dst), "l"(m), "r"(bar), "r"(c0), "r"(c1) : "memory");
}
__device__ __forceinline__ void tma2d_mc(uint32_t dst, const CUtensorMap* m, int c0, int c1, uint32_t bar, uint16_t mask) {
    asm volatile("cp.async.bulk.tensor.2d.shared::cluster.global.mbarrier::complete_tx::bytes.multicast::cluster [%0], [%1, {%3, %4}], [%2], %5;"
                 ::"r"(dst), "l"(m), "r"(bar), "r"(c0), "r"(c1), "h"(mask) : "memory");
}
__device__ __forceinline__ void tma3d(uint32_t dst, const CUtensorMap* m, int c0, int c1, int c2, uint32_t bar) {
    asm volatile("cp.async.bulk.tensor.3d.shared::cluster.global.mbarrier::complete_tx::bytes [%0], [%1, {%3, %4, %5}], [%2];"
                 ::"r"(dst), "l"(m), "r"(bar), "r"(c0), "r"(c1), "r"(c2) : "memory");
}
__device__ __forceinline__ void tma3d_mc(uint32_t dst, const CUtensorMap* m, int c0, int c1, int c2, uint32_t bar, uint16_t mask) {
    asm volatile("cp.async.bulk.tensor.3d.shared::cluster.global.mbarrier::complete_tx::bytes.multicast::cluster [%0], [%1, {%3, %4, %5}], [%2], %6;"
                 ::"r"(dst), "l"(m), "r"(bar), "r"(c0), "r"(c1), "r"(c2), "h"(mask) : "memory");
}
__device__ __forceinline__ void bulk_g2s(uint32_t dst, const void* src, uint32_t bytes, uint32_t bar) {
    asm volatile("cp.async.bulk.shared::cluster.global.mbarrier::complete_tx::bytes [%0], [%1], %2, [%3];"
                 ::"r"(dst), "l"(src), "r"(bytes), "r"(bar) : "memory");
}
__device__ __forceinline__ void prefetch_l2(const void* p) { asm volatile("prefetch.global.L2 [%0];" ::"l"(p)); }
__device__ __forceinline__ void prefetch_tmap(const CUtensorMap* m) { asm volatile("prefetch.tensormap [%0];" ::"l"(m) : "memory"); }

__device__ __forceinline__ void wg_fence() { asm volatile("wgmma.fence.sync.aligned;" ::: "memory"); }
__device__ __forceinline__ void wg_commit() { asm volatile("wgmma.commit_group.sync.aligned;" ::: "memory"); }
template <int N> __device__ __forceinline__ void wg_wait() { asm volatile("wgmma.wait_group.sync.aligned %0;" ::"n"(N) : "memory"); }
__device__ __forceinline__ uint64_t mkdesc(uint32_t addr, uint32_t lbo, uint32_t sbo, uint32_t mode) {
    return (uint64_t)((addr & 0x3FFFF) >> 4) | ((uint64_t)(lbo >> 4) << 16) | ((uint64_t)(sbo >> 4) << 32) | ((uint64_t)mode << 62);
}

__device__ __forceinline__ void mma16816(float (&c)[4], uint32_t a0, uint32_t a1, uint32_t a2, uint32_t a3, uint32_t b0, uint32_t b1) {
    asm("mma.sync.aligned.m16n8k16.row.col.f32.bf16.bf16.f32 {%0,%1,%2,%3},{%4,%5,%6,%7},{%8,%9},{%0,%1,%2,%3};"
                 : "+f"(c[0]), "+f"(c[1]), "+f"(c[2]), "+f"(c[3]) : "r"(a0), "r"(a1), "r"(a2), "r"(a3), "r"(b0), "r"(b1));
}
__device__ __forceinline__ void mma1688(float (&c)[4], uint32_t a0, uint32_t a1, uint32_t b0) {
    asm("mma.sync.aligned.m16n8k8.row.col.f32.bf16.bf16.f32 {%0,%1,%2,%3},{%4,%5},{%6},{%0,%1,%2,%3};"
                 : "+f"(c[0]), "+f"(c[1]), "+f"(c[2]), "+f"(c[3]) : "r"(a0), "r"(a1), "r"(b0));
}
__device__ __forceinline__ void ldsm_x4(uint32_t& r0, uint32_t& r1, uint32_t& r2, uint32_t& r3, uint32_t a) {
    asm volatile("ldmatrix.sync.aligned.m8n8.x4.shared.b16 {%0,%1,%2,%3}, [%4];" : "=r"(r0), "=r"(r1), "=r"(r2), "=r"(r3) : "r"(a) : "memory");
}
__device__ __forceinline__ void ldsm_x4_t(uint32_t& r0, uint32_t& r1, uint32_t& r2, uint32_t& r3, uint32_t a) {
    asm volatile("ldmatrix.sync.aligned.m8n8.x4.trans.shared.b16 {%0,%1,%2,%3}, [%4];" : "=r"(r0), "=r"(r1), "=r"(r2), "=r"(r3) : "r"(a) : "memory");
}
__device__ __forceinline__ void ldsm_x2(uint32_t& r0, uint32_t& r1, uint32_t a) {
    asm volatile("ldmatrix.sync.aligned.m8n8.x2.shared.b16 {%0,%1}, [%2];" : "=r"(r0), "=r"(r1) : "r"(a) : "memory");
}
__device__ __forceinline__ void ldsm_x2_t(uint32_t& r0, uint32_t& r1, uint32_t a) {
    asm volatile("ldmatrix.sync.aligned.m8n8.x2.trans.shared.b16 {%0,%1}, [%2];" : "=r"(r0), "=r"(r1) : "r"(a) : "memory");
}
__device__ __forceinline__ void stsm_x4(uint32_t a, uint32_t r0, uint32_t r1, uint32_t r2, uint32_t r3) {
    asm volatile("stmatrix.sync.aligned.m8n8.x4.shared.b16 [%0], {%1,%2,%3,%4};" ::"r"(a), "r"(r0), "r"(r1), "r"(r2), "r"(r3) : "memory");
}
__device__ __forceinline__ void stsm_x4_t(uint32_t a, uint32_t r0, uint32_t r1, uint32_t r2, uint32_t r3) {
    asm volatile("stmatrix.sync.aligned.m8n8.x4.trans.shared.b16 [%0], {%1,%2,%3,%4};" ::"r"(a), "r"(r0), "r"(r1), "r"(r2), "r"(r3) : "memory");
}
__device__ __forceinline__ void stsm_x2(uint32_t a, uint32_t r0, uint32_t r1) {
    asm volatile("stmatrix.sync.aligned.m8n8.x2.shared.b16 [%0], {%1,%2};" ::"r"(a), "r"(r0), "r"(r1) : "memory");
}
__device__ __forceinline__ uint32_t movm_t(uint32_t a) {
    uint32_t d;
    asm volatile("movmatrix.sync.aligned.m8n8.trans.b16 %0, %1;" : "=r"(d) : "r"(a));
    return d;
}
__device__ __forceinline__ uint32_t lds32(uint32_t a) { uint32_t v; asm volatile("ld.shared.u32 %0, [%1];" : "=r"(v) : "r"(a) : "memory"); return v; }
__device__ __forceinline__ uint32_t ldsv32(uint32_t a) { uint32_t v; asm volatile("ld.volatile.shared.u32 %0, [%1];" : "=r"(v) : "r"(a) : "memory"); return v; }
__device__ __forceinline__ void sts32(uint32_t a, uint32_t v) { asm volatile("st.shared.u32 [%0], %1;" ::"r"(a), "r"(v) : "memory"); }
__device__ __forceinline__ uint4 lds128(uint32_t a) { uint4 v; asm volatile("ld.shared.v4.u32 {%0,%1,%2,%3}, [%4];" : "=r"(v.x), "=r"(v.y), "=r"(v.z), "=r"(v.w) : "r"(a) : "memory"); return v; }
__device__ __forceinline__ void sts128(uint32_t a, uint4 v) { asm volatile("st.shared.v4.u32 [%0], {%1,%2,%3,%4};" ::"r"(a), "r"(v.x), "r"(v.y), "r"(v.z), "r"(v.w) : "memory"); }

__device__ __forceinline__ void stg128(void* p, uint4 v) { asm volatile("st.global.v4.u32 [%0], {%1,%2,%3,%4};" ::"l"(p), "r"(v.x), "r"(v.y), "r"(v.z), "r"(v.w) : "memory"); }

__device__ __forceinline__ uint4 ldg128(const void* p) { uint4 v; asm volatile("ld.global.v4.u32 {%0,%1,%2,%3}, [%4];" : "=r"(v.x), "=r"(v.y), "=r"(v.z), "=r"(v.w) : "l"(p) : "memory"); return v; }
__device__ __forceinline__ uint2 ldg64(const void* p) { uint2 v; asm volatile("ld.global.v2.u32 {%0,%1}, [%2];" : "=r"(v.x), "=r"(v.y) : "l"(p) : "memory"); return v; }
__device__ __forceinline__ uint32_t ldg32(const void* p) { uint32_t v; asm volatile("ld.global.u32 %0, [%1];" : "=r"(v) : "l"(p) : "memory"); return v; }

__device__ __forceinline__ uint32_t pack2(float lo, float hi) {
    uint32_t r;
    asm("cvt.rn.bf16x2.f32 %0, %1, %2;" : "=r"(r) : "f"(hi), "f"(lo));
    return r;
}
__device__ __forceinline__ float bf_lo(uint32_t v) { return __uint_as_float(v << 16); }
__device__ __forceinline__ float bf_hi(uint32_t v) { return __uint_as_float(v & 0xFFFF0000u); }
__device__ __forceinline__ float rbf(float x) { return __uint_as_float(pack2(0.f, x) & 0xFFFF0000u); }
__device__ __forceinline__ float ex2(float x) { float r; asm("ex2.approx.ftz.f32 %0, %1;" : "=f"(r) : "f"(x)); return r; }

__device__ __forceinline__ float2 ln_finish(float sum, float sumsq) {
    const float m = sum * (1.0f / DM);
    const float v = fmaxf(fmaf(sumsq, 1.0f / DM, -m * m), 0.f);
    float s, r;
    asm("sqrt.approx.ftz.f32 %0, %1;" : "=f"(s) : "f"(rbf(rbf(v) + 1e-5f)));
    asm("rcp.approx.ftz.f32 %0, %1;" : "=f"(r) : "f"(rbf(s)));
    return make_float2(m, r);
}
__device__ __forceinline__ uint32_t ln_finish_packed(float sum, float sumsq) {
    const float m = sum * (1.0f / DM);
    const float v = fmaxf(fmaf(sumsq, 1.0f / DM, -m * m), 0.f);
    float s;
    asm("sqrt.approx.ftz.f32 %0, %1;" : "=f"(s) : "f"(rbf(rbf(v) + 1e-5f)));
    return pack2(s, m);
}
__device__ __forceinline__ float frsq(float x) { float r; asm("rsqrt.approx.ftz.f32 %0, %1;" : "=f"(r) : "f"(x)); return r; }
__device__ __forceinline__ float frcp(float x) { float r; asm("rcp.approx.ftz.f32 %0, %1;" : "=f"(r) : "f"(x)); return r; }
__device__ __forceinline__ bool elect_one() {
    uint32_t p;
    asm volatile("{\n.reg .pred p;\nelect.sync _|p, 0xffffffff;\nselp.u32 %0, 1, 0, p;\n}" : "=r"(p));
    return p != 0;
}
__device__ __forceinline__ void cluster_arrive_relaxed() { asm volatile("barrier.cluster.arrive.relaxed.aligned;" ::: "memory"); }
__device__ __forceinline__ void cluster_wait() { asm volatile("barrier.cluster.wait.aligned;" ::: "memory"); }
template<int TA, int TB>
__device__ __forceinline__ void wgmma_n192(float (&d)[96], uint64_t da, uint64_t db, int scale_d) {
  asm volatile("{\n.reg .pred p;\nsetp.ne.b32 p, %98, 0;\n"
    "wgmma.mma_async.sync.aligned.m64n192k16.f32.bf16.bf16 "
    "{%0, %1, %2, %3, %4, %5, %6, %7, %8, %9, %10, %11, %12, %13, %14, %15, %16, %17, %18, %19, %20, %21, %22, %23, %24, %25, %26, %27, %28, %29, %30, %31, %32, %33, %34, %35, %36, %37, %38, %39, %40, %41, %42, %43, %44, %45, %46, %47, %48, %49, %50, %51, %52, %53, %54, %55, %56, %57, %58, %59, %60, %61, %62, %63, %64, %65, %66, %67, %68, %69, %70, %71, %72, %73, %74, %75, %76, %77, %78, %79, %80, %81, %82, %83, %84, %85, %86, %87, %88, %89, %90, %91, %92, %93, %94, %95}, %96, %97, p, 1, 1, %99, %100;\n}\n"
    : "+f"(d[0]), "+f"(d[1]), "+f"(d[2]), "+f"(d[3]), "+f"(d[4]), "+f"(d[5]), "+f"(d[6]), "+f"(d[7]), "+f"(d[8]), "+f"(d[9]), "+f"(d[10]), "+f"(d[11]), "+f"(d[12]), "+f"(d[13]), "+f"(d[14]), "+f"(d[15]), "+f"(d[16]), "+f"(d[17]), "+f"(d[18]), "+f"(d[19]), "+f"(d[20]), "+f"(d[21]), "+f"(d[22]), "+f"(d[23]), "+f"(d[24]), "+f"(d[25]), "+f"(d[26]), "+f"(d[27]), "+f"(d[28]), "+f"(d[29]), "+f"(d[30]), "+f"(d[31]), "+f"(d[32]), "+f"(d[33]), "+f"(d[34]), "+f"(d[35]), "+f"(d[36]), "+f"(d[37]), "+f"(d[38]), "+f"(d[39]), "+f"(d[40]), "+f"(d[41]), "+f"(d[42]), "+f"(d[43]), "+f"(d[44]), "+f"(d[45]), "+f"(d[46]), "+f"(d[47]), "+f"(d[48]), "+f"(d[49]), "+f"(d[50]), "+f"(d[51]), "+f"(d[52]), "+f"(d[53]), "+f"(d[54]), "+f"(d[55]), "+f"(d[56]), "+f"(d[57]), "+f"(d[58]), "+f"(d[59]), "+f"(d[60]), "+f"(d[61]), "+f"(d[62]), "+f"(d[63]), "+f"(d[64]), "+f"(d[65]), "+f"(d[66]), "+f"(d[67]), "+f"(d[68]), "+f"(d[69]), "+f"(d[70]), "+f"(d[71]), "+f"(d[72]), "+f"(d[73]), "+f"(d[74]), "+f"(d[75]), "+f"(d[76]), "+f"(d[77]), "+f"(d[78]), "+f"(d[79]), "+f"(d[80]), "+f"(d[81]), "+f"(d[82]), "+f"(d[83]), "+f"(d[84]), "+f"(d[85]), "+f"(d[86]), "+f"(d[87]), "+f"(d[88]), "+f"(d[89]), "+f"(d[90]), "+f"(d[91]), "+f"(d[92]), "+f"(d[93]), "+f"(d[94]), "+f"(d[95])
    : "l"(da), "l"(db), "r"(scale_d), "n"(TA), "n"(TB));
}

template<int TA, int TB>
__device__ __forceinline__ void wgmma_n48(float (&d)[24], uint64_t da, uint64_t db, int scale_d) {
  asm volatile("{\n.reg .pred p;\nsetp.ne.b32 p, %26, 0;\n"
    "wgmma.mma_async.sync.aligned.m64n48k16.f32.bf16.bf16 "
    "{%0, %1, %2, %3, %4, %5, %6, %7, %8, %9, %10, %11, %12, %13, %14, %15, %16, %17, %18, %19, %20, %21, %22, %23}, %24, %25, p, 1, 1, %27, %28;\n}\n"
    : "+f"(d[0]), "+f"(d[1]), "+f"(d[2]), "+f"(d[3]), "+f"(d[4]), "+f"(d[5]), "+f"(d[6]), "+f"(d[7]), "+f"(d[8]), "+f"(d[9]), "+f"(d[10]), "+f"(d[11]), "+f"(d[12]), "+f"(d[13]), "+f"(d[14]), "+f"(d[15]), "+f"(d[16]), "+f"(d[17]), "+f"(d[18]), "+f"(d[19]), "+f"(d[20]), "+f"(d[21]), "+f"(d[22]), "+f"(d[23])
    : "l"(da), "l"(db), "r"(scale_d), "n"(TA), "n"(TB));
}

__device__ __forceinline__ void wgmma_rs64(float (&d)[32], const uint4& a, uint64_t db, int scale_d) {
  asm volatile("{\n.reg .pred p;\nsetp.ne.b32 p, %37, 0;\n"
    "wgmma.mma_async.sync.aligned.m64n64k16.f32.bf16.bf16 {%0,%1,%2,%3,%4,%5,%6,%7,%8,%9,%10,%11,%12,%13,%14,%15,%16,%17,%18,%19,%20,%21,%22,%23,%24,%25,%26,%27,%28,%29,%30,%31}, {%32,%33,%34,%35}, %36, p, 1, 1, 1;\n}\n"
    : "+f"(d[0]), "+f"(d[1]), "+f"(d[2]), "+f"(d[3]), "+f"(d[4]), "+f"(d[5]), "+f"(d[6]), "+f"(d[7]), "+f"(d[8]), "+f"(d[9]), "+f"(d[10]), "+f"(d[11]), "+f"(d[12]), "+f"(d[13]), "+f"(d[14]), "+f"(d[15]), "+f"(d[16]), "+f"(d[17]), "+f"(d[18]), "+f"(d[19]), "+f"(d[20]), "+f"(d[21]), "+f"(d[22]), "+f"(d[23]), "+f"(d[24]), "+f"(d[25]), "+f"(d[26]), "+f"(d[27]), "+f"(d[28]), "+f"(d[29]), "+f"(d[30]), "+f"(d[31])
    : "r"(a.x), "r"(a.y), "r"(a.z), "r"(a.w), "l"(db), "r"(scale_d));
}

__device__ __forceinline__ void wgmma_rs16(float (&d)[8], const uint4& a, uint64_t db, int scale_d) {
  asm volatile("{\n.reg .pred p;\nsetp.ne.b32 p, %13, 0;\n"
    "wgmma.mma_async.sync.aligned.m64n16k16.f32.bf16.bf16 {%0,%1,%2,%3,%4,%5,%6,%7}, {%8,%9,%10,%11}, %12, p, 1, 1, 1;\n}\n"
    : "+f"(d[0]), "+f"(d[1]), "+f"(d[2]), "+f"(d[3]), "+f"(d[4]), "+f"(d[5]), "+f"(d[6]), "+f"(d[7])
    : "r"(a.x), "r"(a.y), "r"(a.z), "r"(a.w), "l"(db), "r"(scale_d));
}

__device__ const __align__(1024) uint32_t c_fft[11264] = {
0x2ddc2dba,0x2fe62eb5,0x2ed02eb5,0xafffaf6e,0x2e1f2dfe,0x2e3f2fbc,0x2f022ee9,0xad27af30,0x2e5e2e3f,0x1fd92b5e,0x2f302f1a,0x244ea875,0x2e992e7c,0xad96a993,0x2f5a2f46,0x2e992c32,
0xad00ad72,0xa17eac32,0xa17ea515,0xabb79cb6,0xac07ac87,0x2dfe29f1,0x1fd99648,0xafedae99,0xa9f1ab05,0x2fd42fbc,0x26a1244e,0xad96af91,0xa765a8d5,0x2aaa2e3f,0x29932875,0x2515a8d5,
0xae99adfe,0xb000aee9,0xaf6eafbc,0x2c872f30,0xaf80af1a,0xac32af02,0xae7caf02,0xaaaa217e,0xaff4afc9,0x2b5e9cb6,0xad27addc,0xaff4ae7c,0xafedb000,0x2ffc2eb5,0xab05ac5d,0xacd8af5a,
0x2c072d27,0x9fd92bb7,0xadfead00,0x2fed2e1f,0x25db2993,0xaf6eacb0,0xaf6eaed0,0x2c5d2f46,0xa5151648,0xaddcafdd,0xafffafd4,0xac321648,0xabb7a934,0x28d5a814,0xafa0afed,0xaff4af30,
0x2f302e3f,0x2fed2f1a,0x28142b5e,0x2934a875,0x30002fc9,0x26a12ddc,0xa5db1cb6,0x30002e7c,0x2f462fd4,0xaed0aa4e,0xacb0aa4e,0x29932e99,0x2d272e5e,0xae3faffc,0xaf02adfe,0xae1fa814,
0xa9f1acd8,0x26a1ab05,0x2fd42ffc,0xad96afed,0x2515a30e,0x2fff2e1f,0x2ddc2f1a,0x2c32a30e,0x2d272aaa,0x28752e7c,0x28752c32,0x2fa02f80,0x2f912e99,0xaee9a9f1,0xa8141648,0x9fd92c87,
0xafa0ae7c,0xafafaf46,0x2d002993,0xafa0ac32,0xaf91b000,0x244eac5d,0x2fbc2eb5,0xab05af5a,0xac87ae5e,0x30002dfe,0x2f6e2ffc,0x2e992814,0x1cb6a875,0x25152e1f,0x2c322e1f,0x2d722ff4,
0x27652c87,0xa9932a4e,0xaaaaadba,0xa5152c87,0xabb7a44e,0xafa0af30,0x28d59fd9,0xaff4ae5e,0xaf91ae1f,0x2814abb7,0x2ee92d00,0x1fd9ad27,0xaf5aafff,0x2fd42ed0,0x2fd42fe6,0x30002ddc,
0x2f462f6e,0x2c322fdd,0x2e7c2fdd,0xa993b000,0xab5e2934,0xafafacd8,0xad00244e,0x2f1a2dfe,0xaee9afaf,0x2f30a17e,0xadfeaff8,0xafbca30e,0x2c5da765,0xa9f12ddc,0x2d969cb6,0x2c5dacb0,
0x2bb7a993,0x2f1aa515,0x2f1a2765,0xaff4aaaa,0x2e5e2fd4,0xab052dba,0x29342f6e,0x2ee9a6a1,0xadba1fd9,0xa5dbafed,0xafddac07,0xaa4e2dfe,0xacb0aff8,0x2ddc2f02,0x9cb6ae3f,0xa765aff8,
0xaeb5af91,0xaa4eafed,0x9648ae5e,0xac5d2d4d,0x2ddca17e,0x2e7c2e3f,0x2fc92e3f,0x1cb6afa0,0x2bb72fe6,0xaff8a993,0xab5e2aaa,0x2bb72fc9,0xafbcaa4e,0x2f30a5db,0xadfeafdd,0xaee9adba,
0xacd828d5,0xaf91230e,0xaf30af02,0x2c072fa0,0xac5dafff,0x2dbaac32,0x2dbaa515,0xae99addc,0x2fc929f1,0xa9932eb5,0x2aaa2fdd,0x2fe629f1,0xa30e2dfe,0xa17eafed,0xaff8ac07,0xafaf1fd9,
0x2dfe2faf,0x28142ff8,0xae5e217e,0x2ffc230e,0xaf5aa515,0xac87af46,0xa6a1af80,0xaf5a2765,0x1cb6ae99,0x2e7c2dba,0x2fc92dba,0x2ddcac5d,0x2f1a2ee9,0xafafab05,0xad002934,0xab5e2e5e,
0x2dbaa814,0x2fdd9fd9,0x25db2f91,0x2a4eaee9,0x27652faf,0xaf4628d5,0xaf80ae1f,0xa5152faf,0xafa0addc,0x2e3fac32,0x2e3fa515,0xa17eafff,0x2dfea6a1,0xacd82dba,0x244e2f6e,0x29342fd4,
0xad27afc9,0xa30eafff,0x2faf2d72,0xad27ae7c,0x2ffc2a4e,0x28142fdd,0xae5e25db,0x2dfe2dba,0xac5d2c07,0xaa4eaf91,0x9648af30,0xaeb5acd8,0xa993aff4,0x2c322f1a,0x2e7c2f1a,0x2f462bb7,
0xae7c26a1,0xafff1648,0x2d72aa4e,0xafc926a1,0x230eaee9,0x2ff89fd9,0x217e2f91,0x2fafa814,0x2d4d2fa0,0xafed230e,0xae5eaf02,0xaf9128d5,0xb000aaaa,0x2fdda515,0x2fdd2765,0x2f6ea993,
0x9cb63000,0xacb02fd4,0xa7652fd4,0x2ddcaf5a,0x217eaffc,0x2ff4ac07,0x2875afbc,0xaff82934,0xa44e2ff4,0xadfea8d5,0xa9342fa0,0x2cd82bb7,0x25dbafe6,0x16482f46,0x29f1af80,0x25dbafc9,
0x2ff41cb6,0x2e1f2765,0x2e1f2cb0,0xa875addc,0xafbca5db,0x1fd9af5a,0xad4dad96,0xacd82fdd,0x2f5a2934,0xaeb52ee9,0x2c5d2e5e,0x3000ab05,0xaed0ab5e,0x2f80a30e,0xaaaaaf02,0xacb0ab5e,
0x25dbaffc,0x2d96afbc,0x2f5aac07,0xafdd2934,0xaaaa2fa0,0xafc92875,0xafe62875,0x29932d27,0x2d00aed0,0x28d52d72,0x2ff89cb6,0x2d00afe6,0xae5e2d96,0x2d4dafd4,0xaf91a6a1,0xafed29f1,
0xafbca17e,0xad4da875,0x1fd9aff4,0xacd82ff8,0x2e992aaa,0xaa4e2fe6,0xaa4e2fc9,0x2fd4a993,0xacb0ad96,0x2fffac87,0x2d72aeb5,0xa765ad96,0x28752f30,0xab5eac07,0xaf1a2cd8,0xae3f2f91,
0xa9342ff4,0xae5e2fa0,0xaee9a8d5,0x2b052bb7,0x2d96aed0,0x2eb59cb6,0x2c872d72,0x2d96afe6,0xaf802c5d,0x2765af6e,0xa515af6e,0xaf4625db,0x2ff8a44e,0xaff42d4d,0xa8752ffc,0xa17e2ee9,
0x2f5a244e,0x2c5d2934,0xaeb52dfe,0x3000acd8,0xacb0ad00,0x2d72aff8,0x2fffa8d5,0xa765ad00,0x217e2f80,0xaf022515,0xaf02a765,0xaf1a2f46,0x2b05afdd,0xa8142f5a,0x2c072d96,0x2d4d25db,
0x2b5eafe6,0x2f02af80,0x230e2f46,0x2b5eafc9,0xaf302d96,0xacd8a6a1,0x2c07afd4,0xaf9129f1,0x2fdda44e,0xad962ffc,0xaf5a2d4d,0xa5db2ee9,0xad72abb7,0x2e7ca17e,0x2fc9a17e,0x2fffad00,
0xaed0a5db,0xaaaaa9f1,0x2f809648,0xacb0a5db,0x28752e5e,0xaf1a2f91,0xab5ead4d,0xae3f2fed,0x2b05aff8,0x2c072875,0xa8142ff4,0x2d4d217e,0xaf6e2d72,0x2eb5afc9,0x2eb5ae7c,0x2dbaafff,
0xaf802f5a,0xafc92e99,0xafe62e99,0x2f46ad96,0x28d52b05,0xaf022fed,0x230e2cd8,0x2fa0affc,0x2fbcaf02,0xa9342d27,0x2ffcae1f,0x2c07ae3f,0xa6a1ac32,0x2a4e9cb6,0x9648ad72,0xa6a1a515,
0x28752aaa,0xa8d52cb0,0xa8d52ed0,0x2e3faf80,0x2fedaeb5,0x29349648,0x2f30aa4e,0x2814ac5d,0x1648ad4d,0x2e99acd8,0x2c87afbc,0xa9f11fd9,0xafe62d27,0x2fffafaf,0xaddc230e,0xaed02d27,
0x2fd4af30,0x2f6eae5e,0x2dbaa44e,0xa6a19fd9,0x1cb6ad27,0x2fe6aff4,0x2ed0aff4,0xad722b5e,0xafaf2cb0,0x2e1faf46,0xa8d5a993,0xafaf2ed0,0xac072f6e,0x2934ac87,0xaffc2e99,0xafbc3000,
0xa44eab5e,0x2b05ad00,0x2f91afaf,0xafbc2f1a,0xafd42d72,0x1648a765,0x1648acb0,0xafdd2fff,0xac322f5a,0xaaaa26a1,0xaf802c87,0xae7c2f5a,0x2d009fd9,0xae1f2cd8,0xad272fbc,0xabb72d4d,
0xaffc2f02,0xaee92e1f,0x244ead27,0xad4d2e3f,0xa9f12e7c,0xafdd2f80,0xaeb52aaa,0xa9f12c32,0x2d72a5db,0xafe63000,0xaed03000,0x9cb626a1,0x2fa0afbc,0xaf022f91,0x230e2b05,0x28d5a44e,
0x96482c07,0xac872d4d,0xae992b05,0x29f1a814,0x2ed0abb7,0xa9932b5e,0xaf462ff8,0x2cb0abb7,0x2f1aafff,0xa30e2765,0xa30e2cb0,0x2e1fad72,0x1fd9ac5d,0x244e9648,0x2e5eaa4e,0x2f30aeb5,
0x2ff8aed0,0x2e3faddc,0xaf022fff,0x2ff8afe6,0x2d4daf6e,0x2ee9ae99,0xa44e2c87,0x2ffcb000,0xa6a1a814,0x2f6eaf30,0x2dbaa934,0x2fd4afed,0xaf462d00,0x2fc9afa0,0x2fe6afa0,0x2f80afaf,
0x2515ac5d,0x2d72ad96,0x1cb629f1,0x2c32ac5d,0xad002814,0x2d27ad4d,0x2e1fab05,0x2bb7ac07,0xaffc2f1a,0x2cd8ad00,0x2fedafaf,0x2b05ab5e,0xadba2f80,0x2c87acb0,0x2c87aed0,0x2a4eaaaa,
0x2f802f6e,0x2fc92fdd,0x2fe62fdd,0xaf46b000,0x2fa02f91,0x2bb72e5e,0x2ff42fed,0xa8d5ad4d,0x2fbc2faf,0xa934217e,0x2ffc2ff8,0x2c07230e,0x2fd42fc9,0xaf5aad72,0x30002fff,0x2fd42e7c,
0x2bb72aaa,0x2f1a2cb0,0x2f1a2ed0,0xaff4af80,0x2cd82c5d,0x2f303000,0x2f912f5a,0xac07aeb5,0x2dba2d4d,0x25db2cd8,0x2fdd2fbc,0x2a4e9fd9,0x2e7c2e1f,0xad72a875,0x2fff2ff4,0x2fc92e1f,
0xa6a1a934,0x29f1a44e,0x2d962cd8,0xafd4adfe,0x1cb6a17e,0x2fe62e3f,0x2ed02e3f,0xad72afa0,0x28752515,0x2d272f80,0x2fa02f46,0x2875a765,0x2c072a4e,0xa93425db,0x2ffc2fdd,0x2fbc2dba,
0xae5eaf1a,0xa934ae3f,0x2b052875,0xaee9ab5e,0xac5dad72,0x2dba2765,0x2dba2cb0,0xae99afff,0xa765aa4e,0x2f802fd4,0x2f462e99,0x2515aa4e,0x230e9fd9,0x217e2cd8,0x2ff82fbc,0x2faf2d4d,
0xaffcafaf,0xaee9aff8,0x244ea17e,0xad4da30e,0xaf6eafe6,0x25dbaaaa,0x2c5d2993,0xaf6eafc9,0xad72ae99,0x2fe62dba,0x2ed02dba,0x1cb6ac5d,0xa8d5ac07,0x2bb72f30,0x2ff42f91,0x2fa02cd8,
0xadbaac07,0xafddad4d,0xa5dbab05,0xaa4e2814,0xafc9af02,0xaaaaaf1a,0x2993217e,0xafe6af02,0xafa0afff,0x2e3f2765,0x2e3f2cb0,0xa17ead72,0xad4daeb5,0x2e5e3000,0x2fed2f5a,0x2f912c5d,
0xa17e2765,0xad001cb6,0xabb7addc,0xa17e2cb0,0xad4daa4e,0xaee9afdd,0x244ea5db,0xaffcadba,0xafd4aee9,0x29f1a934,0x2d962b05,0xa6a1ae5e,0xaf46aff4,0x2fc92f1a,0x2fe62f1a,0x2f802bb7,
0x2cb02eb5,0x1cb62dba,0xaddcaf6e,0x27652eb5,0xa30e2814,0xaff8ad4d,0xa17eab05,0xafafac07,0xadfeab5e,0xa44eae3f,0x2cd82875,0xa934af1a,0xb000af80,0x2fdd2cb0,0x2fdd2ed0,0x2f6e2aaa,
0x2d723000,0x25152fd4,0x2c322fd4,0x1cb6af5a,0xae1f9fd9,0xae3faee9,0xaf02a814,0x2d272f91,0xacd8aff4,0x2ffc28d5,0xab05afa0,0xafedabb7,0x2e992515,0xad962aaa,0x2f5a2993,0x2e99a765,
0x2ff42ddc,0x2e1f2ed0,0x2e1f2fe6,0xa875afff,0xa8142c87,0xaffca9f1,0xadfe1648,0x2e5e2e99,0xaf5aaf30,0x2eb5a814,0xac5dafed,0xb000a934,0x2c32a8d5,0xa9932e3f,0x2f462875,0x2e7ca8d5,
0x2e991fd9,0x30002814,0x2f6e2ee9,0xac87af91,0x29932fa0,0xaed02875,0xacb02875,0x2f462d27,0xaff4ac32,0x2b5eaddc,0xad27afff,0xaff4a515,0x244ead96,0x1fd92fd4,0x2f3026a1,0x2e5ea9f1,
0x2814ad27,0x2dfeabb7,0x2ffc2d00,0xae5eae1f,0x2e992f80,0xaa4e2e7c,0xaa4e2c32,0x2fd42aaa,0xae7c1648,0x9cb6afdd,0xaddcafd4,0xafc91648,0xa875af91,0x2b5e2fbc,0x2f1a244e,0x2e3fab05,
0xab05aff4,0x244eafa0,0x2fbc28d5,0xaf91abb7,0x30002c32,0x26a12fff,0xa5db2ddc,0x30002515,0xaaaa2c5d,0xac32af6e,0xae7caf6e,0xaf8025db,0xad27afed,0x2e3f2dfe,0x2f021fd9,0x2e1fac07,
0xaf5aae5e,0xac5daf30,0x2eb59fd9,0xb000a44e,0x2e7ca30e,0x2ddc2e1f,0x1cb62f1a,0x2fc9a30e,0x217e2f46,0xaf02acb0,0xaf02aed0,0xaf1a2993,0xaf30ae99,0x2fbc29f1,0x2ee99648,0x2dfeac87,
0xafa0a515,0xafafa993,0x2d00aaaa,0xafa02765,0x2934ad96,0x2fed26a1,0x28142fd4,0x2f30a9f1,0x2c872fed,0xb0009fd9,0xaf6eadfe,0xae992c07,0xafffabb7,0x2fe6a17e,0x2ed0a17e,0x2ddcad00,
0xac322c87,0xaf462a4e,0x2993adba,0xae7c2c87,0xa875afed,0x2f1aab05,0x2b5e2ffc,0x2e3facd8,0x2f302e1f,0xaee92bb7,0xafbcad00,0xadfe2d27,0xaf6e9cb6,0x2eb5ac32,0x2eb5a515,0x2dbaad72,
0xaaaa2f5a,0xaed02e99,0xacb02e99,0x2f80ad96,0x2b5eaf30,0x2fafa44e,0x2d00ae5e,0xaf1a9fd9,0xac072f02,0xab05ad27,0xad4d2e1f,0x28142e3f,0x2c5daed0,0xa9f12fff,0x2d96addc,0x2c5dafe6,
0x28752f80,0xa8d52fe6,0xa8d52fc9,0x2e3faf46,0xa44eafd4,0x2f91adba,0x2b05af6e,0xafbc26a1,0x96482ffc,0xae99a44e,0xac872ee9,0x29f12d4d,0x2515aff8,0x1cb62f02,0x2d72ae3f,0x2c32aff8,
0x2eb52b05,0x2a4e2cd8,0x16482fed,0x2c5daffc,0xad72ad27,0x2cb0aff4,0x2765aff4,0xafff2b5e,0x2bb72e7c,0xaff82aaa,0xab5e2f80,0x2bb72c32,0xa814af6e,0x2b052c87,0x2d4dae99,0x2c07b000,
0x2feda8d5,0x2f30a30e,0x29342f02,0x2814afa0,0xafd49cb6,0x1648aed0,0x1648afe6,0xafdd2d72,0x2ed029f1,0xaf462eb5,0xa9932fdd,0x2cb029f1,0xad00ad4d,0x2e1f244e,0x2d27aee9,0x2bb7affc,
0x2d4daf02,0x2fbcae1f,0x2cd82d27,0x9fd9ae3f,0xaf5a2cb0,0xac87a993,0xa6a1af46,0xaf5a2ed0,0x2fffa5db,0xacb03000,0xa7653000,0x2d7226a1,0xaf1aa814,0x2fafa934,0x2d00af30,0x2b5eafed,
0x1648afbc,0x2c87affc,0x2e992934,0xa9f1ac07,0xac322faf,0xaf8028d5,0xaaaaae1f,0xae7c2faf,0x2f1aad72,0xa30e2ed0,0xa30e2fe6,0x2e1f1cb6,0xaffc26a1,0x2fedadba,0x2cd8af6e,0x2b05afd4,
0xad27ac32,0xa30ead72,0x2faf9cb6,0xad27a515,0x1fd92f6e,0xafbc2e99,0xacd8ac87,0xad4d3000,0x2c5dafbc,0x2a4e2b05,0x16482f91,0x2eb5a44e,0xaf802d00,0x2ed0afa0,0x2cb0afa0,0x2aaaafaf,
0xafe626a1,0xaddc1648,0x2fffaa4e,0xaed026a1,0x2d002c07,0xad272ffc,0xae1fa934,0xabb72fbc,0x1fd9afa0,0x2e5ea30e,0x244e2f02,0x2f30a8d5,0xadba2f46,0x2c87afe6,0x2c87afc9,0x2a4eaf80,
0xafff2d96,0xae7c2c5d,0xafc92c5d,0x2d72a9f1,0xa17e2dfe,0xaff42fbc,0xa8752ee9,0x2ff8af30,0x2fedad00,0xad4d2f1a,0x2f91ab5e,0x2e5eafaf,0x25dbae7c,0x16482993,0x29f1af46,0x25dbac32,
0xae3f2fff,0xaff82fc9,0xaff82e7c,0x2f02ad72,0x2c0725db,0xadfe2f5a,0x9fd92d96,0x2fedafdd,0x2f6eaf91,0xa6a12c07,0x2fd4acd8,0x2dbaaf30,0xa765ab5e,0x2aaaa30e,0x2993af02,0x2515ab5e,
0xa5db2dfe,0xad962ee9,0xaf5a2fbc,0x2fddaf30,0x2f46ab5e,0xa7652bb7,0x25152bb7,0x2f80aff8,0x2d00afc9,0x28d59cb6,0x2ff8addc,0x2d00ae7c,0xacd89648,0x2dfeac5d,0x2934aeb5,0x244eaa4e,
0x2c07217e,0x9fd92875,0xadfe2ff4,0x2fedaff8,0x2fddaf46,0x29f1a515,0x29f12765,0x2eb5af80,0x2515ad96,0x2ddcac87,0x2fffaeb5,0x2c32ad96,0xaf022b05,0x2fa0aee9,0x28d5ae5e,0x230ea934,
0x2f91ad00,0x2cd8ab5e,0xac072f1a,0x2f30afaf,0x2d96afc9,0x2eb5addc,0x2c879cb6,0x2d96ae7c,0xa993a6a1,0x2fc9af5a,0x2fe6af5a,0x2aaaac87,0xaff82e5e,0x2ff4affc,0x2875adfe,0x217ea814,
0x2f6eafed,0x2fd4af91,0xa6a12d4d,0x2dbaae5e,0x2515ad00,0x2fffaff8,0x2ddca8d5,0x2c32ad00,0xae1f2993,0x2fafafe6,0x2fafafc9,0x28d5aaaa,0xaf912fdd,0x2ee9af5a,0x2814ad96,0x1fd9a5db,
0x2b5eae7c,0x2f02af46,0x230e2993,0x2b5eac32,0xab059648,0x2e5eaeb5,0x2ee9ac5d,0x2934aa4e,0xafdd2e5e,0x2d96adfe,0x2f5aaffc,0x25dba814,0xaddc2faf,0x2cb0ad27,0x2765ad27,0x1cb6a30e,
0xa765a5db,0x2993a9f1,0x2aaa9648,0x2515a5db,0xaf022cd8,0x28d5a934,0x2fa0adfe,0x230ea44e,0xaf912ff8,0x2814a875,0x2ee9aff4,0x1fd9a17e,0xaa4e2ddc,0x26a1a765,0x26a1acb0,0x16489cb6,
0x2d722d96,0x25152c5d,0x2c322c5d,0x1cb6a9f1,0x2d272d4d,0xad00a814,0x2bb72c07,0x2e1f2b05,0x2cd82d00,0xaffcaf1a,0x2b052b5e,0x2fed2faf,0x2c872cb0,0xadbaaf80,0x2a4e2aaa,0x2c872ed0,
0x2e3f2ddc,0x2ff82ed0,0x2ff82fe6,0xaf02afff,0x2ee92e99,0x2d4d2f6e,0x2ffc3000,0xa44eac87,0x2f6e2f30,0xa6a12814,0x2fd42fed,0x2dba2934,0x2fc92fa0,0xaf46ad00,0x2f802faf,0x2fe62fa0,
0xac87ad4d,0x9648ac07,0x29f12814,0xae99ab05,0xa993ab5e,0x2ed02bb7,0x2cb02bb7,0xaf46aff8,0xa30ea765,0x2f1a2fff,0x2e1f2d72,0xa30eacb0,0x244e1648,0x1fd92c5d,0x2f302eb5,0x2e5e2a4e,
0xaee9ae1f,0xaffcaf02,0xad4dae3f,0x244e2d27,0xafddaf80,0xa9f1ae7c,0xa9f1ac32,0xaeb5aaaa,0xafe6b000,0x2d7225db,0x9cb6a6a1,0xaed0b000,0xaf02af91,0x2fa02fbc,0x28d5244e,0x230eab05,
0x2b052d00,0xa44e2b5e,0xafbcaf1a,0x2f912faf,0x16482765,0xafd4ad72,0xafddafff,0x16482cb0,0xaaaaa6a1,0xac32af5a,0xae7caf5a,0xaf80ac87,0xae1facd8,0x2d001fd9,0xabb7ad4d,0xad27afbc,
0x2f6e2e5e,0x2fd42f30,0xa6a11fd9,0x2dba244e,0x2fe62ff4,0x1cb62d27,0xad72ab5e,0x2ed02ff4,0x2e1f2f46,0xafafacb0,0xafafaed0,0xa8d52993,0x29342c87,0xac07af6e,0xafbcb000,0xaffcae99,
0xa8d5acb0,0x2875aaaa,0x2e3f2f80,0xa8d5aed0,0x29341648,0x2fed2eb5,0x28142c5d,0x2f302a4e,0x2e992cd8,0x16482d4d,0xa9f19fd9,0x2c872fbc,0x2fff2faf,0xafe6ad27,0xaed0ad27,0xaddca30e,
0xafc9ae99,0xaf80af5a,0x2f462d96,0xafe6ae99,0xaf02afed,0x28d5ab05,0x2fa02ffc,0x230eacd8,0xa934ad27,0x2fbc2f02,0x2c072e3f,0x2ffc2e1f,0x2a4e1cb6,0xa6a12c32,0xa6a12515,0x96482d72,
0xaaaa29f1,0xaed025db,0xacb025db,0x2f801648,0xaf1aaf91,0x2875ae5e,0xae3fafed,0xab5e2d4d,0x2c07a875,0x2b052ff8,0x2d4da17e,0xa814aff4,0x2eb52fc9,0xaf6ead72,0x2dba2fff,0x2eb52e7c,
0x2f022f80,0x2b5e2fe6,0x2b5e2fc9,0x230eaf46,0xacd826a1,0xaf30ad96,0xaf91a9f1,0x2c072fd4,0xad96affc,0x2fdd244e,0xa5dbaee9,0xaf5aad4d,0x2e7c217e,0xad722bb7,0x2fff2d00,0x2fc9217e,
0x2c5da934,0x2f5aa44e,0x30002cd8,0xaeb5adfe,0x2d722ff8,0xacb02d00,0xa7652d00,0x2fff28d5,0xaf02a515,0x217eaf80,0xaf1aaf46,0xaf022765,0xa814af5a,0x2b052fdd,0x2d4da5db,0x2c07ad96,
0xae5eafa0,0xa934aff4,0x2b05abb7,0xaee928d5,0x2eb51cb6,0x2d962ed0,0x2d962fe6,0x2c87ad72,0x27652f6e,0xaf80ac5d,0xaf46a5db,0xa5152f6e,0xaff4ad4d,0x2ff8244e,0xa17eaee9,0xa875affc,
0xad4d2875,0xafbc217e,0xacd8aff8,0x1fd92ff4,0xaa4eafe6,0x2e99aaaa,0x2fd42993,0xaa4eafc9,0x2fff2c87,0xacb02d96,0xa7652d96,0x2d722eb5,0xab5e2c07,0x2875af30,0xae3faf91,0xaf1aacd8,
0x2d962fbc,0x25db2ffc,0xafdda934,0x2f5a2c07,0xafc9a875,0xaaaaafa0,0x2993ad27,0xafe6a875,0x28d5ad72,0x2d002ed0,0x2d002fe6,0x2ff81cb6,0x2d4d2fd4,0xae5ead96,0xafeda9f1,0xaf9126a1,
0x2e1fa765,0x2ff49cb6,0xa8752ddc,0x2e1facb0,0x1fd92f5a,0xafbc25db,0xacd8afdd,0xad4d2d96,0xaeb5aee9,0x2f5aa934,0x30002b05,0x2c5dae5e,0x2f80230e,0xaed02b5e,0xacb02b5e,0xaaaa2f02,
0xacb0afd4,0x9cb6b000,0x2ddc2f5a,0xa765afd4,0x2ff42c07,0x217e2ffc,0xaff8a934,0x28752fbc,0xadfe28d5,0xa44eaff4,0x2cd8abb7,0xa934afa0,0x1648af46,0x25db2fe6,0x25db2fc9,0x29f12f80,
0xafff9648,0xae7ca6a1,0xafc9a6a1,0x2d722a4e,0x2ff81fd9,0x230e2ee9,0x2faf2814,0x217eaf91,0xafeda30e,0x2d4dafa0,0xaf91a8d5,0xae5e2f02,0x2fdd2515,0xb0002aaa,0x2f6e2993,0x2fdda765,
0xa30e2fff,0xad272fc9,0xad272e7c,0x2fafad72,0x2814afdd,0x2ffcaa4e,0x2dfeadba,0xae5ea5db,0xaa4e2f91,0xac5dac07,0xaeb52cd8,0x96482f30,0x2c32af1a,0xa9932ff4,0x2f46abb7,0x2e7caf1a,
0x2fdd1fd9,0x2dba2814,0x2a4e2ee9,0x25dbaf91,0xaf46a8d5,0x2765afaf,0xa515afaf,0xaf802e1f,0x2e3f2c32,0xafa02ddc,0xa17e2fff,0x2e3f2515,0xacd8adba,0x2dfe26a1,0x2934afd4,0x244eaf6e,
0x2814aff8,0x2dfeafaf,0x2ffca30e,0xae5ea17e,0xac872f46,0xaf5a2515,0xaf5aa765,0xa6a12f80,0x2e7cadba,0x1cb62e99,0x2ddc2c5d,0x2fc9adba,0xafaf2b05,0x2f1aaee9,0xab5eae5e,0xad00a934,
0xaf91a30e,0xacd8a8d5,0x2c07afa0,0xaf302f02,0x2dba2c32,0xac5d2fff,0xae992ddc,0x2dba2515,0xa993aeb5,0x2fc9a9f1,0x2fe6a9f1,0x2aaaafdd,0xa17e2fed,0xa30eadfe,0xafaf9fd9,0xaff82c07,
0xaa4e2fed,0xaeb52f91,0xac5dad4d,0x96482e5e,0x2e7cae3f,0x2ddc217e,0x1cb62fa0,0x2fc9ae3f,0xaff82993,0x2bb7afe6,0x2bb7afc9,0xab5eaaaa,0x2f3025db,0xafbc2a4e,0xaee92dba,0xadfe2fdd,
0x2f1a2515,0x2bb72993,0xaff42aaa,0x2f1aa765,0xab05adba,0x2e5eafd4,0x2ee926a1,0x2934af6e,0xa5db2fed,0xadba9fd9,0xaa4eadfe,0xafdd2c07,0x2ddcaf02,0xacb02ff8,0xa7652ff8,0x9cb62e3f,
0x2c32afdd,0x2f46af6e,0xa9933000,0x2e7cafdd,0xafaf2cd8,0xab5ea934,0x2f1aadfe,0xad00a44e,0x2f30217e,0xaee92faf,0xafbc230e,0xadfe2ff8,0xa9f1addc,0x2c5d2765,0x2c5d2cb0,0x2d961cb6,
0xa993aa4e,0x2765ac87,0xa515ac87,0xaaaa2dba,0xafa02f30,0xabb7244e,0xaff42e5e,0x28d51fd9,0x28142bb7,0xaf912e1f,0x1fd92d27,0x2ee9ad00,0x2fd4aed0,0xaf5a2fff,0x3000addc,0x2fd4afe6,
0xafaf2f46,0xafa02e7c,0xafa02c32,0x2d00a993,0x244e2c5d,0xaf913000,0xab052f5a,0x2fbcaeb5,0x3000adfe,0xac872e5e,0x2e99a814,0x2f6eaffc,0x2515ae1f,0x1cb62875,0x2d72aff4,0x2c32ae1f,
0x26a12b05,0xa9f12cd8,0xad962fed,0x2fd4affc,0x2fffae1f,0x2515230e,0x2c32230e,0x2ddcaf1a,0x2875ae7c,0x2d27aaaa,0x2fa0af80,0x2875ac32,0xaee929f1,0x2f91ae99,0x9fd9ac87,0xa8149648,
0x2fedaf1a,0x2f30ae3f,0x29342875,0x2814ab5e,0x26a1addc,0x3000afc9,0x3000ae7c,0xa5db9cb6,0xaed02a4e,0x2f46afd4,0x2993ae99,0xacb02a4e,0xae3f2ffc,0x2d27ae5e,0xae1f2814,0xaf022dfe,
0x9fd9abb7,0x2c07ad27,0x2fedae1f,0xadfe2d00,0xaf6e2cb0,0x25dba993,0x2c5daf46,0xaf6e2ed0,0xaddc2fdd,0xa5159648,0xac329648,0xafff2fd4,0x28d52814,0xabb72934,0xaff42f30,0xafa02fed,
0xb0002ee9,0xae992dfe,0x2c87af30,0xaf6e2fbc,0xac322f02,0xaf802f1a,0xaaaaa17e,0xae7c2f02,0x2b5e1cb6,0xaff42fc9,0xaff42e7c,0xad272ddc,0x2ffcaeb5,0xafed3000,0xacd82f5a,0xab052c5d,
0xa17e2c32,0xad002d72,0xabb71cb6,0xa17e2515,0x2dfea9f1,0xac072c87,0xafed2e99,0x1fd91648,0x2fd4afbc,0xa9f12b05,0xad962f91,0x26a1a44e,0x2aaaae3f,0xa76528d5,0x251528d5,0x2993a875,
0x2fe6aeb5,0x2ddcadba,0xafff2f6e,0x2ed0aeb5,0x2e3fafbc,0x2e1fadfe,0xad272f30,0x2f02aee9,0x1fd9ab5e,0x2e5eae3f,0x244e2875,0x2f30af1a,0xad962993,0x2e99ae7c,0x2e99ac32,0x2f5aaf46,
0x299329f1,0xa76525db,0x251525db,0x2aaa1648,0x28d52934,0xaf02acd8,0x230e244e,0x2fa02dfe,0x28142875,0xaf91aff8,0x1fd9217e,0x2ee92ff4,0x26a12765,0xaa4eaddc,0x16481cb6,0x26a12cb0,
0x2f022f46,0x2b5e2e7c,0x2b5e2c32,0x230ea993,0x2e5e2eb5,0xab051648,0x29342a4e,0x2ee92c5d,0x2d962dfe,0xafddae5e,0x25db2814,0x2f5a2ffc,0x2cb02d27,0xaddcafaf,0x1cb6230e,0x27652d27,
0x2fd42f91,0x2f6e2fed,0x2dba2e5e,0xa6a1ad4d,0x2fff2ff8,0x25152d00,0x2c322d00,0x2ddc28d5,0x2faf2fe6,0xae1fa993,0x28d52aaa,0x2faf2fc9,0x2ee92f5a,0xaf91afdd,0x1fd925db,0x28142d96,
0x2cd82b5e,0x2f912d00,0x2f302faf,0xac07af1a,0x2eb52ddc,0x2d962fc9,0x2d962e7c,0x2c871cb6,0x2fc92f5a,0xa99326a1,0x2aaa2c87,0x2fe62f5a,0x2ff42ffc,0xaff8ae5e,0x217e2814,0x28752dfe,
0x9fd9a875,0x2c07a17e,0x2fed2ff8,0xadfeaff4,0x29f12515,0x2fdd2f46,0x2eb52f80,0x29f1a765,0x2ddc2c87,0x25152d96,0x2c322d96,0x2fff2eb5,0x2fa02ee9,0xaf02ab05,0x230e2934,0x28d52e5e,
0xad96aee9,0xa5dbadfe,0x2fdd2f30,0xaf5aafbc,0xa765abb7,0x2f462b5e,0x2f802ff8,0x2515abb7,0x28d51cb6,0x2d002fc9,0x2d002e7c,0x2ff82ddc,0x2dfe2c5d,0xacd81648,0x244e2a4e,0x29342eb5,
0xaff8afc9,0xae3fafff,0x2f022d72,0xaff8ae7c,0xadfeaf5a,0x2c07a5db,0x2fed2fdd,0x9fd9ad96,0xa6a1ac07,0x2f6e2f91,0x2dba2f30,0x2fd42cd8,0x2aaa230e,0xa7652b5e,0x25152b5e,0x29932f02,
0xae7cac5d,0xafffad96,0x2d7229f1,0xafc9ac5d,0xaff4afbc,0xa17eadfe,0x2ff82f30,0xa875aee9,0xad4daf1a,0x2fed2d00,0x2e5e2faf,0x2f912b5e,0x1648a993,0x25db2e7c,0x25db2c32,0x29f12f46,
0xaddc9648,0xafe6a6a1,0xaed0a6a1,0x2fff2a4e,0xad27affc,0x2d00ac07,0xabb7afbc,0xae1f2934,0x2e5e230e,0x1fd92fa0,0x2f3028d5,0x244eaf02,0x2c872fe6,0xadbaaf46,0x2a4e2f80,0x2c872fc9,
0xa30e2d72,0xad272c32,0xad272515,0x2faf1cb6,0xafbcae99,0x1fd9af6e,0xad4db000,0xacd82c87,0x2a4eab05,0x2c5d2fbc,0x2eb5244e,0x1648af91,0x2ed02fa0,0xaf80ad00,0x2aaa2faf,0x2cb02fa0,
0x2c872ffc,0x16482fbc,0xa9f12c07,0x2e99a934,0xaf80a8d5,0xac32afaf,0xae7cafaf,0xaaaa2e1f,0xa30eaed0,0x2f1a2d72,0x2e1f9cb6,0xa30eafe6,0x2fed2dba,0xaffca6a1,0x2b052fd4,0x2cd82f6e,
0x2fbc2e1f,0x2d4d2f02,0x9fd92e3f,0x2cd8ad27,0xac872993,0xaf5aacb0,0xaf5aaed0,0xa6a12f46,0xacb0b000,0x2fff25db,0x2d72a6a1,0xa765b000,0x2faf2934,0xaf1a2814,0x2b5e2fed,0x2d002f30,
0x2f30230e,0x2fed28d5,0x28142fa0,0x2934af02,0x16482ed0,0xafd41cb6,0xafddad72,0x16482fe6,0xaf46aeb5,0x2ed0a9f1,0x2cb0a9f1,0xa993afdd,0x2e1fa44e,0xad002d4d,0x2bb72ffc,0x2d272ee9,
0x2a4eacd8,0x2eb5ab05,0x2c5d2ffc,0x1648afed,0x2cb02ff4,0xad722d27,0xafffab5e,0x27652ff4,0xaff8aaaa,0x2bb7ae7c,0x2bb7ac32,0xab5eaf80,0x2b05ac87,0xa8142f6e,0x2c073000,0x2d4d2e99,
0xa8d5afe6,0x2875af80,0x2e3f2f46,0xa8d5afc9,0x2f912dba,0xa44e2fd4,0xafbca6a1,0x2b052f6e,0xae99244e,0x9648affc,0x29f1ad4d,0xac87aee9,0x1cb6af02,0x25152ff8,0x2c322ff8,0x2d722e3f,
0xaed0ae99,0xaaaaaf5a,0x2f802d96,0xacb0ae99,0x2faf244e,0x2b5e2f30,0xaf1a1fd9,0x2d002e5e,0xab052d27,0xac07af02,0x2814ae3f,0xad4dae1f,0xa9f1afff,0x2c5d2ed0,0x2c5d2fe6,0x2d962ddc,
0xaf46aa4e,0xac32ac87,0xae7cac87,0x29932dba,0x2f1a2b05,0xa8752fed,0x2e3f2cd8,0x2b5eaffc,0xaee9abb7,0x2f30ae1f,0xadfead27,0xafbc2d00,0x2eb52c32,0xaf6e1cb6,0x2dba2d72,0x2eb52515,
0xafaf2993,0xafa02515,0xafa0a765,0x2d002aaa,0x2feda6a1,0x29342d96,0x2f3029f1,0x2814afd4,0xb0001fd9,0x2c87afed,0xae99ac07,0xaf6e2dfe,0x2fe6217e,0xafff2bb7,0x2ddc2d00,0x2ed0217e,
0xac5d2f30,0xaf5a2e5e,0xb000244e,0x2eb51fd9,0x2ddcae1f,0x2e7c230e,0x2fc9230e,0x1cb6af1a,0xaf022cb0,0x217eaf46,0xaf1aa993,0xaf022ed0,0x2fbca9f1,0xaf302e99,0x2dfe2c87,0x2ee91648,
0x244e2fa0,0xab052ff4,0xaf912bb7,0x2fbca8d5,0x26a1afff,0x3000ac32,0x3000a515,0xa5dbaddc,0xac322f6e,0xaaaaac5d,0xaf80a5db,0xae7c2f6e,0x2e3fadfe,0xad272fed,0x2e1f2c07,0x2f029fd9,
0x2dfe2bb7,0x28142d27,0xae5e2e1f,0x2ffcad00,0xaa4eae7c,0x2e99af80,0x2fd4aaaa,0xaa4eac32,0x9cb62fdd,0xae7c9648,0xafc99648,0xaddc2fd4,0x2b5eafbc,0xa8752f91,0x2e3f2b05,0x2f1aa44e,
0x3000a814,0x2e999fd9,0xac872f91,0x2f6eaee9,0xaed0a875,0x2993afa0,0x2f46ad27,0xacb0a875,0x2b5e2ddc,0xaff42c32,0xaff42515,0xad272fff,0x1fd9afd4,0x244e2d96,0x2e5e29f1,0x2f30a6a1,
0x2e1faed0,0x2ff4addc,0xa8752fff,0x2e1fafe6,0xaffc29f1,0xa814ac87,0x2e5eae99,0xadfe9648,0x2eb52814,0xaf5a2f30,0xb0002934,0xac5d2fed,0xa993ae3f,0x2c3228d5,0x2e7c28d5,0x2f46a875,
0x2515afd4,0x2d72b000,0x1cb62f5a,0x2c32afd4,0xae3f2ee9,0xae1f1fd9,0x2d27af91,0xaf022814,0x2ffca8d5,0xacd82ff4,0xafed2bb7,0xab052fa0,0xad96aaaa,0x2e99a515,0x2e992765,0x2f5aa993,
0x1cb6adba,0x2cb0aeb5,0x2765aeb5,0xaddc2f6e,0xaff82d4d,0xa30ea814,0xafaf2c07,0xa17e2b05,0xa44e2e3f,0xadfe2b5e,0xa9342f1a,0x2cd8a875,0x2fddacb0,0xb0002f80,0x2f6eaaaa,0x2fddaed0,
0xad009cb6,0xa17ea765,0xa17eacb0,0xabb72ddc,0xaee92fdd,0xad4d2a4e,0xaffc2dba,0x244e25db,0x29f12934,0xafd42ee9,0xa6a12e5e,0x2d96ab05,0x2fc9af1a,0xaf462ff4,0x2f80abb7,0x2fe6af1a,
0xafdd2d4d,0xadba2c07,0xaa4ea814,0xa5db2b05,0xaaaa2f1a,0xafc92f02,0xafe62f02,0x2993a17e,0x2e3fa765,0xafa02fff,0xa17e2d72,0x2e3facb0,0x2e5eb000,0xad4d2eb5,0x2f91ac5d,0x2fedaf5a,
0xaee92ff8,0xaffc2faf,0xad4d230e,0x244e217e,0x25db2aaa,0xaf6e2fe6,0xaf6e2fc9,0x2c5da993,0x2fe6adba,0xad722e99,0x1cb62c5d,0x2ed0adba,0x2bb7af30,0xa8d52c07,0x2fa0acd8,0x2ff4af91,
0xa9342e3f,0xae5e2f1a,0xaee92b5e,0x2b05a875,0x2dbaa765,0xac5d2d72,0xae992fff,0x2dbaacb0,0x2f80afd4,0xa7652a4e,0x25152a4e,0x2f46ae99,0x217eacd8,0x230e1fd9,0x2fafad4d,0x2ff8afbc,
0x29f1244e,0xa6a12934,0xafd42dfe,0x2d96acd8,0x2fe6ae3f,0x1cb6217e,0xad722fa0,0x2ed0ae3f,0x2d27af80,0x2875a515,0x28752765,0x2fa0af46,0xa934a5db,0x2c07aa4e,0x2fbcadba,0x2ffcafdd,
0x2f1aacb0,0x2bb7aaaa,0xaff42f80,0x2f1aaed0,0x2f30b000,0x2cd8ac5d,0xac072eb5,0x2f91af5a,0x25dbacd8,0x2dbaad4d,0x2a4e1fd9,0x2fddafbc,0xad722875,0x2e7cae1f,0x2fc9ae1f,0x2fffaff4,
0x2fc9afdd,0x2f80af6e,0xaf463000,0x2fe6afdd,0x2bb7ae5e,0x2fa0af91,0xa8d52d4d,0x2ff4afed,0xa934a17e,0x2fbcafaf,0x2c07a30e,0x2ffcaff8,0xaf5a2d72,0x2fd4afc9,0x2fd4ae7c,0x3000afff,
0x3c003c00,0x3bff3c00,0x3c003c00,0x3bfa3bfd,0x3c003c00,0x3bef3bf5,0x3c003c00,0x3bde3be7,0x3c003c00,0x3bc83bd4,0x3c003c00,0x3bac3bbb,0x3c003c00,0x3b8b3b9d,0x3bff3c00,0x3b653b79,
0x3c003c00,0x3bff3c00,0x3c003c00,0x3bf83bfd,0x3bff3c00,0x3bea3bf2,0x3bff3bff,0x3bd63be1,0x3bfe3bff,0x3bba3bc9,0x3bfd3bfe,0x3b983baa,0x3bfc3bfd,0x3b6f3b84,0x3bfb3bfc,0x3b3f3b58,
0x3c003c00,0x3bff3c00,0x3bff3c00,0x3bf63bfc,0x3bfe3bff,0x3be53bef,0x3bfd3bfe,0x3bcc3bda,0x3bfb3bfc,0x3bab3bbc,0x3bf93bfa,0x3b813b97,0x3bf63bf7,0x3b4f3b69,0x3bf23bf4,0x3b163b33,
0x3c003c00,0x3bff3c00,0x3bff3c00,0x3bf53bfb,0x3bfd3bfe,0x3be03bec,0x3bfa3bfc,0x3bc23bd2,0x3bf63bf8,0x3b9a3baf,0x3bf23bf4,0x3b683b82,0x3bec3bef,0x3b2c3b4b,0x3be53be9,0x3ae83b0b,
0x3c003c00,0x3bfe3c00,0x3bfe3bff,0x3bf23bfa,0x3bfb3bfd,0x3bda3be8,0x3bf63bf9,0x3bb73bca,0x3bf03bf4,0x3b873ba0,0x3be83bed,0x3b4c3b6b,0x3bdf3be4,0x3b073b2b,0x3bd43bda,0x3ab63ae0,
0x3c003c00,0x3bfe3c00,0x3bfd3bff,0x3bf03bf9,0x3bf93bfb,0x3bd43be4,0x3bf23bf6,0x3bab3bc1,0x3be83bed,0x3b733b91,0x3bdd3be3,0x3b2f3b53,0x3bcf3bd6,0x3ade3b08,0x3bbf3bc7,0x3a813ab1,
0x3c003c00,0x3bfe3c00,0x3bfc3bfe,0x3bee3bf8,0x3bf63bf9,0x3bce3be0,0x3bec3bf1,0x3b9e3bb7,0x3bdf3be6,0x3b5e3b80,0x3bcf3bd7,0x3b103b39,0x3bbc3bc6,0x3ab33ae3,0x3ba53bb1,0x3a493a7f,
0x3bff3c00,0x3bfe3c00,0x3bfb3bfe,0x3beb3bf7,0x3bf23bf7,0x3bc63bdb,0x3be53bed,0x3b903bad,0x3bd43bdd,0x3b473b6e,0x3bbf3bca,0x3aee3b1d,0x3ba53bb2,0x3a853abc,0x3b873b97,0x3a0d3a4b,
0x3bfd3c00,0x3bfa3c00,0x3be83bf6,0x3bcc3be9,0x3bbf3bd6,0x3b713ba4,0x3b813ba2,0x3aeb3b33,0x3b2f3b5a,0x3a3d3a99,0x3acb3aff,0x396b39d8,0x3a543a92,0x387a38f6,0x39cd3a13,0x36dd37ee,
0x3bfd3c00,0x3bfa3c00,0x3be53bf4,0x3bc83be7,0x3bb73bd1,0x3b653b9d,0x3b713b97,0x3ad53b22,0x3b163b46,0x3a193a7c,0x3aa53ae0,0x393739ad,0x3a213a65,0x383538ba,0x398b39d8,0x36313753,
0x3bfd3c00,0x3bf93c00,0x3be23bf3,0x3bc33be5,0x3bae3bcb,0x3b593b95,0x3b603b8a,0x3abd3b11,0x3afb3b30,0x39f43a5e,0x3a7e3abf,0x39023980,0x39eb3a37,0x37dd387c,0x3946399b,0x358136b5,
0x3bfc3c00,0x3bf93c00,0x3bdf3bf1,0x3bbf3be3,0x3ba53bc6,0x3b4c3b8c,0x3b4f3b7d,0x3aa53aff,0x3ade3b1a,0x39cd3a3f,0x3a543a9c,0x38cc3951,0x39b33a07,0x374e383d,0x38fd395b,0x34cf3614,
0x3bfc3c00,0x3bf83c00,0x3bdc3bf0,0x3bba3be1,0x3b9c3bc0,0x3b3f3b84,0x3b3d3b70,0x3a8c3aed,0x3ac13b02,0x39a63a1f,0x3a293a78,0x38943922,0x397939d4,0x36bb37f9,0x38b23918,0x341a3570,
0x3bfc3c00,0x3bf83c00,0x3bd83bee,0x3bb53bdf,0x3b923bb9,0x3b323b7b,0x3b2a3b62,0x3a733ad9,0x3aa23ae9,0x397d39fe,0x39fc3a52,0x385a38f1,0x393c399f,0x36253775,0x386538d3,0x32c634c9,
0x3bfb3c00,0x3bf73c00,0x3bd43bed,0x3bb03bdc,0x3b873bb2,0x3b243b72,0x3b163b53,0x3a583ac6,0x3a813ad0,0x395439dc,0x39cd3a2b,0x382038bf,0x38fd3969,0x358d36ee,0x3815388c,0x31533420,
0x3bfb3c00,0x3bf63c00,0x3bd03beb,0x3bab3bda,0x3b7c3bab,0x3b163b69,0x3b013b43,0x3a3d3ab1,0x3a603ab5,0x392939ba,0x399d3a02,0x37c8388c,0x38bc3930,0x34f33665,0x37853842,0x2fbd32ea,
0x3bf63c00,0x3bf03c00,0x3ba53bd7,0x3b733bc1,0x3b073b5f,0x3a813b08,0x3a213a9c,0x392939e1,0x38fd3996,0x36ff385d,0x374e3858,0x327c3529,0x345735da,0xa9b12d1a,0x2cce3191,0xb49fb160,
0x3bf53c00,0x3bef3c00,0x3b9f3bd5,0x3b6c3bbe,0x3af73b55,0x3a6f3afc,0x3a043a87,0x390739c7,0x38d13972,0x36993832,0x36d23822,0x316c34b1,0x3371354c,0xad65297f,0x27763036,0xb552b2b9,
0x3bf53c00,0x3bef3c00,0x3b9a3bd2,0x3b653bbb,0x3ae83b4b,0x3a5c3af0,0x39e73a71,0x38e539ad,0x38a3394d,0x36313807,0x365437d8,0x305b3438,0x323234bd,0xafef1e48,0xa4522db0,0xb602b408,
0x3bf43c00,0x3bee3c00,0x3b943bd0,0x3b5e3bb7,0x3ad83b41,0x3a493ae3,0x39c93a5a,0x38c13992,0x38743927,0x35c837b7,0x35d4376a,0x2e91337d,0x30f0342c,0xb13ba7da,0xac0629e3,0xb6afb4b1,
0x3bf33c00,0x3bed3c00,0x3b8e3bcd,0x3b573bb4,0x3ac73b36,0x3a353ad6,0x39aa3a43,0x389e3976,0x38453900,0x355e375e,0x355236f9,0x2c6a3288,0x2f593334,0xb27cac51,0xaef51a48,0xb759b558,
0x3bf23c00,0x3bec3c00,0x3b873bca,0x3b4f3bb1,0x3ab63b2b,0x3a213ac9,0x398b3a2b,0x387a395b,0x381538d8,0x34f33705,0x34cf3687,0x28843191,0x2cce320d,0xb3baaeaa,0xb0f0a91b,0xb7feb5fd,
0x3bf23c00,0x3beb3c00,0x3b813bc7,0x3b473bad,0x3aa53b20,0x3a0d3abc,0x396b3a13,0x3855393e,0x37c838b0,0x348736aa,0x344b3614,0x16483099,0x288430e4,0xb47bb080,0xb263ad4c,0xb850b69e,
0x3bf13c00,0x3bea3c00,0x3b7a3bc4,0x3b3f3baa,0x3a933b14,0x39f83aae,0x394a39fa,0x38303922,0x37643887,0x341a364e,0x3389359f,0xa81f2f40,0x9cb62f72,0xb517b1aa,0xb3d3b004,0xb89eb73d,
0x3be93c00,0x3be13c00,0x3b373ba6,0x3af13b86,0x39e33aa0,0x392e3a27,0x380a3905,0x3599380d,0x335935f1,0x217f31db,0xac382d4c,0xb546b12e,0xb5b1b2d2,0xb90cb7cd,0xb8eab7d8,0xbadbba0b,
0x3be83c00,0x3be03c00,0x3b2f3ba2,0x3ae83b82,0x39cd3a92,0x39163a17,0x37c838e7,0x354637d8,0x327c3593,0xa4523115,0xae5f2aac,0xb5c8b226,0xb648b3f7,0xb94ab828,0xb933b838,0xbb0aba43,
0x3be73c00,0x3bdf3c00,0x3b273b9e,0x3ade3b7d,0x39b83a83,0x38fd3a07,0x377a38c9,0x34f33796,0x319e3534,0xa9b1304e,0xb042257f,0xb648b31b,0xb6ddb48d,0xb986b867,0xb979b881,0xbb35ba78,
0x3be63c00,0x3bde3c00,0x3b1e3b9b,0x3ad53b79,0x39a13a74,0x38e539f6,0x372c38ab,0x349f3753,0x30be34d5,0xac9c2f0e,0xb153a0b6,0xb6c6b408,0xb76fb51d,0xb9c0b8a6,0xb9bcb8c9,0xbb5cbaaa,
0x3be53c00,0x3bdd3c00,0x3b163b97,0x3acb3b74,0x398b3a65,0x38cc39e5,0x36dd388c,0x344b3710,0x2fbd3475,0xae5f2d7e,0xb263a91b,0xb742b481,0xb7feb5ab,0xb9f8b8e2,0xb9fcb90e,0xbb7fbad9,
0x3be43c00,0x3bdc3c00,0x3b0d3b93,0x3ac13b70,0x39743a56,0x38b239d4,0x368d386d,0x33eb36cc,0x2dfb3414,0xb0102bd9,0xb371ac83,0xb7bdb4f9,0xb845b637,0xba2db91d,0xba39b951,0xbb9ebb05,
0x3be33c00,0x3bda3c00,0x3b043b8f,0x3ab63b6b,0x395d3a47,0x389939c3,0x363c384d,0x33403687,0x2c383365,0xb0f028b6,0xb43eae78,0xb81ab570,0xb889b6c1,0xba60b956,0xba73b992,0xbbb8bb2e,
0x3be23c00,0x3bd93c00,0x3afb3b8a,0x3aac3b67,0x39463a37,0x387f39b1,0x35eb382d,0x32943642,0x28e832a1,0xb1cf2248,0xb4c3b036,0xb855b5e5,0xb8ccb748,0xba90b98d,0xbaa9b9d0,0xbbcfbb53,
0x3c003c00,0x3bfe3c00,0x3c003c00,0x3bf73bfc,0x3c003c00,0x3beb3bf2,0x3c003c00,0x3bd93be3,0x3c003c00,0x3bc13bce,0x3c003c00,0x3ba53bb4,0x3c003c00,0x3b823b94,0x3bff3bff,0x3b5b3b6f,
0x3c003c00,0x3bfe3c00,0x3c003c00,0x3bf53bfb,0x3bff3c00,0x3be63bee,0x3bff3bff,0x3bcf3bdb,0x3bfe3bfe,0x3bb23bc1,0x3bfd3bfe,0x3b8e3ba1,0x3bfc3bfd,0x3b643b7a,0x3bfb3bfb,0x3b333b4c,
0x3c003c00,0x3bfe3c00,0x3bff3c00,0x3bf33bf9,0x3bfe3bff,0x3be03beb,0x3bfd3bfd,0x3bc53bd3,0x3bfb3bfc,0x3ba13bb4,0x3bf83bf9,0x3b753b8c,0x3bf53bf7,0x3b413b5c,0x3bf23bf3,0x3b063b25,
0x3c003c00,0x3bfd3c00,0x3bff3bff,0x3bf03bf8,0x3bfc3bfe,0x3bda3be6,0x3bf93bfb,0x3bb93bca,0x3bf53bf7,0x3b8e3ba5,0x3bf03bf3,0x3b5a3b75,0x3beb3bee,0x3b1c3b3c,0x3be43be7,0x3ad53afa,
0x3c003c00,0x3bfd3c00,0x3bfe3bff,0x3bee3bf7,0x3bfa3bfc,0x3bd33be2,0x3bf53bf8,0x3bac3bc1,0x3bee3bf2,0x3b7a3b94,0x3be63beb,0x3b3c3b5c,0x3bdd3be2,0x3af43b19,0x3bd13bd7,0x3aa13acb,
0x3bff3c00,0x3bfc3c00,0x3bfc3bfe,0x3beb3bf5,0x3bf73bfa,0x3bcb3bdd,0x3bf03bf4,0x3b9e3bb6,0x3be63beb,0x3b643b82,0x3bda3be0,0x3b1c3b41,0x3bcb3bd3,0x3ac83af4,0x3bba3bc3,0x3a683a9a,
0x3bff3c00,0x3bfb3bff,0x3bfb3bfd,0x3be73bf3,0x3bf43bf8,0x3bc33bd7,0x3be93bef,0x3b8f3bab,0x3bdb3be3,0x3b4c3b6f,0x3bca3bd3,0x3afa3b25,0x3bb63bc1,0x3a9a3acb,0x3b9f3bab,0x3a2c3a65,
0x3bff3c00,0x3bfb3bff,0x3bf93bfd,0x3be43bf2,0x3bf03bf5,0x3bba3bd1,0x3be23be9,0x3b7f3b9f,0x3bcf3bd9,0x3b333b5b,0x3bb93bc5,0x3ad53b06,0x3b9e3bac,0x3a683aa1,0x3b7f3b8f,0x39ec3a2c,
0x3bfa3bff,0x3bf33bff,0x3be03bf0,0x3bba3bdc,0x3bb13bcb,0x3b533b8c,0x3b6e3b92,0x3ac33b10,0x3b183b45,0x3a0c3a6c,0x3aaf3ae5,0x393139a3,0x3a343a73,0x383938b9,0x39a939f1,0x36513767,
0x3bf93bff,0x3bf23bfe,0x3bdc3bee,0x3bb43bd9,0x3ba73bc5,0x3b453b82,0x3b5c3b85,0x3aa93afd,0x3afb3b2e,0x39e43a4c,0x3a863ac3,0x38fa3973,0x39fd3a44,0x37e03878,0x396339b2,0x359c36c3,
0x3bf93bff,0x3bf13bfe,0x3bd83beb,0x3bae3bd6,0x3b9d3bbe,0x3b373b78,0x3b493b76,0x3a8f3ae9,0x3add3b16,0x39bb3a2a,0x3a5b3a9f,0x38c03942,0x39c43a12,0x374b3836,0x39193971,0x34e4361d,
0x3bf83bff,0x3bf03bfe,0x3bd33be9,0x3ba73bd3,0x3b923bb6,0x3b273b6e,0x3b353b67,0x3a733ad4,0x3abe3afd,0x39913a08,0x3a2e3a79,0x38853910,0x398839de,0x36b237e6,0x38cd392d,0x34293573,
0x3bf73bff,0x3bee3bfe,0x3bcf3be7,0x3ba13bcf,0x3b873baf,0x3b183b64,0x3b203b57,0x3a573abe,0x3a9d3ae2,0x396539e4,0x39ff3a51,0x384938dc,0x394939a7,0x3617375c,0x387e38e6,0x32d834c6,
0x3bf63bff,0x3bed3bfe,0x3bca3be4,0x3b9a3bcc,0x3b7b3ba6,0x3b073b58,0x3b0a3b47,0x3a3a3aa8,0x3a7b3ac6,0x393939bf,0x39cf3a28,0x380b38a7,0x3908396e,0x357936cf,0x382c389d,0x315a3417,
0x3bf53bff,0x3bec3bfe,0x3bc53be2,0x3b933bc8,0x3b6e3b9e,0x3af73b4d,0x3af43b35,0x3a1c3a91,0x3a573aa9,0x390b399a,0x399c39fd,0x37993871,0x38c53934,0x34d8363f,0x37af3851,0x2fb032cc,
0x3bf43bff,0x3beb3bfe,0x3bbf3bdf,0x3b8c3bc5,0x3b613b95,0x3ae53b41,0x3adc3b23,0x39fd3a79,0x3a323a8b,0x38dc3973,0x396739d1,0x37183839,0x388038f7,0x343535ae,0x37023803,0x2ca93166,
0x3be93bfd,0x3bdd3bfc,0x3b853bc1,0x3b413b9e,0x3ad43b35,0x3a343ac8,0x39de3a61,0x38c53988,0x38ac394b,0x361737e0,0x36963800,0x30863435,0x3322351a,0xaecf2484,0x267b2ffb,0xb590b352,
0x3be83bfd,0x3bdb3bfc,0x3b7d3bbd,0x3b383b99,0x3ac13b29,0x3a1e3ab9,0x39bd3a48,0x389f396a,0x387b3923,0x35a83783,0x3611378e,0x2ecf336b,0x31d53484,0xb0b8a54d,0xa5b22d26,0xb645b45a,
0x3be63bfd,0x3bd93bfc,0x3b753bb9,0x3b2e3b94,0x3aaf3b1c,0x3a083aa9,0x399c3a2e,0x3878394b,0x384938fa,0x35373724,0x358a3718,0x2c903269,0x308633d9,0xb207ab8e,0xac77289d,0xb6f6b508,
0x3be53bfd,0x3bd73bfb,0x3b6d3bb5,0x3b253b8f,0x3a9b3b0f,0x39f13a9a,0x397a3a14,0x3851392d,0x381638cf,0x34c636c3,0x350236a1,0x289d3166,0x2e6b32a7,0xb352ae39,0xaf7ea052,0xb7a4b5b3,
0x3be33bfd,0x3bd53bfb,0x3b653bb0,0x3b1b3b8a,0x3a883b01,0x39d93a8a,0x395739f9,0x3829390d,0x37c538a4,0x34543662,0x34783628,0x12483061,0x2b8e3172,0xb44eb055,0xb141aac5,0xb826b65c,
0x3be23bfd,0x3bd33bfb,0x3b5c3bac,0x3b103b85,0x3a733af4,0x39c13a79,0x393439de,0x380038ed,0x375c3878,0x33c035ff,0x33d935ae,0xa86b2eb6,0x2484303c,0xb4f0b18b,0xb2bfae39,0xb878b702,
0x3be03bfc,0x3bd13bfb,0x3b533ba7,0x3b063b7f,0x3a5f3ae5,0x39a93a68,0x391039c1,0x37af38cd,0x36f1384c,0x32d8359c,0x32bf3531,0xac772ca9,0xa6162e07,0xb590b2bf,0xb41db086,0xb8c8b7a4,
0x3bde3bfc,0x3bcf3bfb,0x3b4b3ba3,0x3afb3b7a,0x3a4a3ad7,0x39913a57,0x38eb39a5,0x375c38ac,0x3684381e,0x31ee3537,0x31a434b4,0xaeb62934,0xac2b2b2a,0xb62eb3f1,0xb4d8b1ee,0xb914b821,
0x3bcd3bfa,0x3bbb3bf8,0x3af03b74,0x3a933b43,0x39783a46,0x38a239b0,0x3707388b,0x344736e0,0x310334d2,0xacdb2e39,0xb07a2052,0xb690b3e5,0xb6c9b490,0xb991b87e,0xb95eb86e,0xbb30ba79,
0x3bcb3bfa,0x3bb93bf8,0x3ae53b6e,0x3a863b3c,0x395e3a34,0x3885399c,0x36b23869,0x33d93696,0x3016346c,0xaeb62c90,0xb197a616,0xb713b472,0xb761b526,0xb9ccb8be,0xb9a5b8b9,0xbb58baad,
0x3bc93bfa,0x3bb63bf8,0x3ada3b68,0x3a793b35,0x39443a22,0x38693988,0x365c3846,0x3322364b,0x2e523405,0xb04829ca,0xb2b3ab2a,0xb793b4f0,0xb7f6b5b9,0xba05b8fc,0xb9e8b901,0xbb7dbadd,
0x3bc73bfa,0x3bb43bf7,0x3acf3b62,0x3a6c3b2e,0x392a3a10,0x384c3973,0x36053824,0x326935ff,0x2c77333a,0xb13424e9,0xb3cdada3,0xb809b56d,0xb844b64b,0xba3cb939,0xba28b947,0xbb9dbb0a,
0x3bc53bf9,0x3bb13bf7,0x3ac33b5c,0x3a5f3b27,0x391039fd,0x382e395e,0x35ae3800,0x31b035b3,0x29343269,0xb21f9f12,0xb472afb0,0xb846b5e8,0xb88bb6da,0xba70b973,0xba65b98a,0xbbb9bb34,
0x3bc23bf9,0x3baf3bf7,0x3ab73b56,0x3a513b20,0x38f539ea,0x38113949,0x355537ba,0x30f63567,0x21e43197,0xb309a839,0xb4fcb0de,0xb883b662,0xb8cfb767,0xbaa1b9ab,0xba9db9ca,0xbbd0bb5a,
0x3bc03bf9,0x3bac3bf7,0x3aab3b50,0x3a443b19,0x38d939d7,0x37e63934,0x34fc3772,0x303c351a,0xa48430c5,0xb3f1ab8e,0xb584b1e2,0xb8beb6da,0xb912b7f1,0xbacfb9e2,0xbad2ba08,0xbbe3bb7c,
0x3bbe3bf9,0x3ba93bf6,0x3a9f3b49,0x3a363b12,0x38be39c4,0x37a9391e,0x34a23729,0x2f0134cc,0xa9fd2fe2,0xb46cad71,0xb60bb2e4,0xb8f7b750,0xb953b83c,0xbafaba16,0xbb03ba42,0xbbf1bb9a,
0x96488000,0xa6ad8000,0x9cb69a48,0xad00aaac,0x9fdb9e48,0xb029aeaa,0xa17fa0b6,0xb1cfb0fd,0xa311a248,0xb371b2a1,0xa452a3db,0xb487b420,0xa51ba4b6,0xb552b4ed,0xa5e4a57f,0xb61ab5b6,
0x9cb68000,0xa7768000,0xa311a0b6,0xad97ab75,0xa5e4a4b6,0xb0a6af72,0xa81fa711,0xb27cb191,0xa94da8b6,0xb426b365,0xaa7aa9e3,0xb50bb499,0xaba7ab11,0xb5ebb57c,0xac6aac1f,0xb6c6b659,
0x9fdb8000,0xa81f8000,0xa5e4a3db,0xae2dac1f,0xa8e8a7da,0xb122b01d,0xaadea9e3,0xb328b226,0xac6aabd9,0xb493b414,0xad65ace7,0xb58db511,0xae5fade2,0xb682b608,0xaf59aedc,0xb76fb6f9,
0xa17f8000,0xa8848000,0xa81fa57f,0xaec3ac83,0xaadea97f,0xb19eb080,0xacceac1f,0xb3d3b2b9,0xae2dad7e,0xb4ffb475,0xaf8baedc,0xb60eb587,0xb074b01d,0xb715b693,0xb122b0cb,0xb80ab796,
0xa3118000,0xa8e88000,0xa94da711,0xaf59ace7,0xac6aab11,0xb219b0e4,0xae2dad4c,0xb43eb34c,0xafefaf0e,0xb56ab4d5,0xb0d7b067,0xb68db5fd,0xb1b6b147,0xb7a6b71b,0xb294b226,0xb85ab817,
0xa4528000,0xa94d8000,0xaa7aa852,0xafefad4c,0xad65ac51,0xb294b147,0xaf8bae78,0xb493b3df,0xb0d7b04e,0xb5d4b534,0xb1e8b160,0xb70ab670,0xb2f7b26f,0xb81ab7a1,0xb402b37d,0xb8a8b862,
0xa51b8000,0xa9b18000,0xaba7a91b,0xb042adb0,0xae5fad1a,0xb30fb1aa,0xb074afa4,0xb4e7b438,0xb1b6b115,0xb63cb593,0xb2f7b257,0xb785b6e3,0xb41ab396,0xb85fb812,0xb4b7b469,0xb8f3b8ab,
0xa5e48000,0xaa168000,0xac6aa9e3,0xb08dae14,0xaf59ade2,0xb389b20d,0xb122b067,0xb53ab481,0xb294b1db,0xb6a4b5f1,0xb402b34c,0xb7feb753,0xb4b7b45d,0xb8a3b852,0xb56ab511,0xb93cb8f1,
0xaa7a8000,0xacce8000,0xb0d7ae78,0xb328b0cb,0xb402b26f,0xb5dfb4bd,0xb58db4c9,0xb805b6f9,0xb70ab64e,0xb902b887,0xb83ab7c2,0xb9e3b976,0xb8e5b891,0xbaa2ba47,0xb982b935,0xbb3abaf3,
0xaade8000,0xad008000,0xb122aedc,0xb371b0fd,0xb43eb2d2,0xb61ab4ed,0xb5dfb511,0xb82ab73d,0xb76fb6aa,0xb92eb8b0,0xb874b817,0xba11b9a4,0xb924b8ce,0xbaceba74,0xb9c5b976,0xbb60bb1d,
0xab438000,0xad338000,0xb16caf40,0xb3bab12e,0xb47bb334,0xb654b51d,0xb631b558,0xb850b780,0xb7d2b705,0xb958b8d8,0xb8adb84d,0xba3db9d0,0xb962b909,0xbaf7baa0,0xba04b9b5,0xbb83bb43,
0xaba78000,0xad658000,0xb1b6afa4,0xb402b160,0xb4b7b396,0xb68db54c,0xb682b59f,0xb874b7c2,0xb81ab75e,0xb982b900,0xb8e5b881,0xba67b9fa,0xb99db943,0xbb1ebac9,0xba41b9f2,0xbba1bb67,
0xac068000,0xad978000,0xb201b004,0xb426b191,0xb4f3b3f7,0xb6c6b57c,0xb6d2b5e5,0xb899b802,0xb84ab7b7,0xb9aab927,0xb91bb8b5,0xba90ba23,0xb9d6b97b,0xbb42baf0,0xba7aba2b,0xbbbcbb86,
0xac388000,0xadc98000,0xb24bb036,0xb44bb1c3,0xb52fb42c,0xb6ffb5ab,0xb721b62b,0xb8bcb822,0xb87ab807,0xb9d2b94d,0xb94fb8e7,0xbab6ba4b,0xba0db9b1,0xbb63bb14,0xbab0ba62,0xbbd2bba2,
0xac6a8000,0xadfb8000,0xb294b067,0xb46fb1f4,0xb56ab45d,0xb737b5da,0xb76fb670,0xb8e0b842,0xb8a8b832,0xb9f8b972,0xb982b918,0xbadbba71,0xba41b9e5,0xbb81bb36,0xbae1ba95,0xbbe3bbbb,
0xac9c8000,0xae2d8000,0xb2deb099,0xb493b226,0xb5a5b48d,0xb76fb608,0xb7bdb6b5,0xb902b862,0xb8d6b85d,0xba1db996,0xb9b3b948,0xbafeba95,0xba73ba17,0xbb9cbb55,0xbb10bac6,0xbbf1bbd0,
0xae5f8000,0xafef8000,0xb4b7b257,0xb5d4b3df,0xb7a6b637,0xb8a8b7a1,0xb924b881,0xba1db96d,0xba41b9ba,0xbb32bab5,0xbb1ebab8,0xbbd6bb93,0xbbb3bb72,0xbbfebbf9,0xbbfabbe1,0xbba9bbe3,
0xae918000,0xb0108000,0xb4dbb288,0xb5f7b408,0xb7ddb665,0xb8c1b7cd,0xb946b8a0,0xba39b989,0xba64b9dc,0xbb4abad0,0xbb3dbad9,0xbbe2bba6,0xbbc8bb8c,0xbbf9bbfe,0xbbffbbee,0xbb8bbbd2,
0xaec38000,0xb0298000,0xb4ffb2b9,0xb61ab420,0xb80ab693,0xb8dbb7f9,0xb966b8bf,0xba54b9a4,0xba85b9fe,0xbb60bae9,0xbb59baf9,0xbbedbbb7,0xbbd9bba4,0xbbf0bc00,0xbc00bbf8,0xbb6abbbe,
0xaef58000,0xb0428000,0xb523b2ea,0xb63cb438,0xb825b6c1,0xb8f3b812,0xb986b8dd,0xba6fb9be,0xbaa5ba1f,0xbb76bb02,0xbb73bb17,0xbbf5bbc7,0xbbe7bbb9,0xbbe4bbff,0xbbfcbbfe,0xbb45bba6,
0xaf278000,0xb05b8000,0xb546b31b,0xb65fb451,0xb840b6ee,0xb90cb828,0xb9a6b8fb,0xba89b9d8,0xbac4ba3f,0xbb89bb1a,0xbb8bbb33,0xbbfbbbd5,0xbbf2bbcb,0xbbd6bbfb,0xbbf4bc00,0xbb1bbb8a,
0xaf598000,0xb0748000,0xb56ab34c,0xb682b469,0xb85ab71b,0xb924b83d,0xb9c5b918,0xbaa2b9f2,0xbae1ba5e,0xbb9cbb30,0xbba1bb4e,0xbbffbbe1,0xbbfabbdb,0xbbc3bbf5,0xbbe7bbfe,0xbaeebb6b,
0xaf8b8000,0xb08d8000,0xb58db37d,0xb6a4b481,0xb874b748,0xb93cb852,0xb9e3b935,0xbababa0b,0xbafeba7c,0xbbacbb46,0xbbb5bb67,0xbc00bbeb,0xbbffbbe8,0xbbaebbec,0xbbd7bbf9,0xbabdbb49,
0xafbd8000,0xb0a68000,0xb5b1b3ae,0xb6c6b499,0xb88eb775,0xb954b867,0xba00b951,0xbad1ba23,0xbb18ba99,0xbbbcbb5a,0xbbc6bb7d,0xbbffbbf3,0xbc00bbf2,0xbb96bbe0,0xbbc2bbf0,0xba89bb22,
0xb0be8000,0xb1858000,0xb6e8b4b1,0xb7f3b570,0xb96bb87c,0xba19b91d,0xbae8ba3b,0xbb7fbae6,0xbbc9bb6e,0xbc00bbdd,0xbbfcbbf9,0xbb8ebbe5,0xbb7abbd1,0xba35bafc,0xba50baf9,0xb820b93e,
0xb0d78000,0xb19e8000,0xb70ab4c9,0xb80ab587,0xb982b891,0xba2db930,0xbafeba52,0xbb8ebaf9,0xbbd6bb80,0xbc00bbe6,0xbbf6bbfd,0xbb76bbda,0xbb5cbbc0,0xba00bad6,0xba15bacc,0xb79bb8fb,
0xb0f08000,0xb1b68000,0xb72cb4e1,0xb81ab59f,0xb999b8a6,0xba41b943,0xbb13ba69,0xbb9cbb0b,0xbbe0bb91,0xbbfebbed,0xbbeebc00,0xbb5cbbcd,0xbb3abbab,0xb9c9baae,0xb9d6ba9c,0xb6f4b8b5,
0xb1098000,0xb1cf8000,0xb74eb4f9,0xb82ab5b6,0xb9afb8ba,0xba54b956,0xbb27ba7f,0xbba9bb1d,0xbbe9bba0,0xbbfbbbf4,0xbbe3bc00,0xbb3fbbbe,0xbb16bb95,0xb990ba83,0xb994ba69,0xb648b86d,
0xb1228000,0xb1e88000,0xb76fb511,0xb83ab5ce,0xb9c5b8ce,0xba67b969,0xbb3aba95,0xbbb5bb2e,0xbbf1bbaf,0xbbf6bbf8,0xbbd7bbfe,0xbb21bbad,0xbaeebb7b,0xb954ba56,0xb94fba33,0xb599b822,
0xb13b8000,0xb2018000,0xb790b529,0xb84ab5e5,0xb9dab8e2,0xba7ab97b,0xbb4cbaaa,0xbbc0bb3e,0xbbf7bbbc,0xbbefbbfc,0xbbc8bbfb,0xbb01bb9b,0xbac4bb5f,0xb916ba27,0xb907b9fa,0xb4e7b7ac,
0xb1538000,0xb2198000,0xb7b2b540,0xb85ab5fd,0xb9f0b8f6,0xba8cb98d,0xbb5ebabf,0xbbcbbb4e,0xbbfcbbc9,0xbbe7bbff,0xbbb7bbf6,0xbadebb86,0xba97bb41,0xb8d6b9f6,0xb8bcb9be,0xb432b710,
0xb16c8000,0xb2328000,0xb7d2b558,0xb86ab614,0xba04b909,0xba9eb99f,0xbb6fbad3,0xbbd4bb5d,0xbbfebbd4,0xbbdebc00,0xbba3bbee,0xbababb70,0xba67bb20,0xb894b9c3,0xb86fb980,0xb2f7b670,
0x98b69248,0xa901a2ad,0x9d7f9bdb,0xadd5ac2b,0xa0529f12,0xb093af7e,0xa1e4a11b,0xb238b166,0xa376a2ad,0xb3d9b309,0xa484a420,0xb4bab454,0xa54da4e9,0xb584b520,0xa616a5b2,0xb64bb5e8,
0x9f1298b6,0xa998a376,0xa420a1e4,0xae84aca9,0xa67ba54d,0xb11cb02f,0xa86ba7a8,0xb2f0b207,0xa998a901,0xb460b3d9,0xaac5aa2f,0xb543b4d2,0xabf2ab5c,0xb622b5b3,0xac90ac44,0xb6fcb690,
0xa1e49bdb,0xaa2fa420,0xa6dfa4e9,0xaf33ad26,0xa966a86b,0xb1a4b09f,0xab5caa61,0xb3a8b2a7,0xaca9ac2b,0xb4d2b454,0xada3ad26,0xb5cbb54f,0xae9dae20,0xb6beb645,0xaf97af1a,0xb7a9b734,
0xa4209d7f,0xaac5a484,0xa8cfa6df,0xafe2ada3,0xab8eaa2f,0xb22cb10f,0xad26ac77,0xb42fb346,0xae84add5,0xb543b4ba,0xafe2af33,0xb651b5cb,0xb09fb048,0xb756b6d4,0xb14db0f6,0xb829b7d5,
0xa54d9f12,0xab5ca4e9,0xaa2fa86b,0xb048ae20,0xacdbabf2,0xb2b3b17f,0xae9dadbc,0xb48ab3e5,0xb02faf7e,0xb5b3b520,0xb10fb09f,0xb6d4b645,0xb1eeb17f,0xb7ebb761,0xb2ccb25d,0xb87bb839,
0xa67ba052,0xabf2a54d,0xab8ea966,0xb09fae9d,0xadeeacdb,0xb33ab1ee,0xb00aaf01,0xb4e4b441,0xb11cb093,0xb622b584,0xb22cb1a4,0xb756b6be,0xb33ab2b3,0xb83eb7eb,0xb423b3c0,0xb8cab885,
0xa7a8a11b,0xac44a5b2,0xac77aa61,0xb0f6af1a,0xaf01adbc,0xb3c0b25d,0xb0c5b023,0xb53db490,0xb207b166,0xb690b5e8,0xb346b2a7,0xb7d5b734,0xb441b3e5,0xb885b839,0xb4deb490,0xb917b8cf,
0xa86ba1e4,0xac90a616,0xad26ab5c,0xb14daf97,0xb00aae9d,0xb423b2cc,0xb17fb0c5,0xb596b4de,0xb2f0b238,0xb6fcb64b,0xb42fb3a8,0xb829b7a9,0xb4e4b48a,0xb8cab87b,0xb596b53d,0xb961b917,
0xacdba67b,0xaf33a8cf,0xb1a4b00a,0xb429b1fa,0xb466b33a,0xb66db54f,0xb5eeb52c,0xb846b783,0xb767b6ad,0xb93db8c5,0xb866b80e,0xba16b9ae,0xb90db8bb,0xbacbba75,0xb9a7b95c,0xbb5abb18,
0xad26a6df,0xaf7ea901,0xb1fab048,0xb454b238,0xb4a8b3a8,0xb6adb584,0xb645b579,0xb86eb7ca,0xb7d0b70d,0xb96ab8f0,0xb8a2b846,0xba44b9db,0xb94eb8fa,0xbaf7baa2,0xb9eab99e,0xbb7ebb40,
0xad71a744,0xafc9a934,0xb251b086,0xb47eb276,0xb4eab40b,0xb6ebb5b9,0xb69bb5c5,0xb895b809,0xb81cb76c,0xb995b919,0xb8dcb87e,0xba70ba08,0xb98cb936,0xbb1fbacd,0xba2ab9de,0xbb9ebb65,
0xadbca7a8,0xb00aa966,0xb2a7b0c5,0xb4a8b2b3,0xb52cb441,0xb729b5ee,0xb6f1b611,0xb8bbb82c,0xb84eb7ca,0xb9bfb942,0xb914b8b4,0xba9aba32,0xb9c8b971,0xbb44baf5,0xba66ba1a,0xbbbabb86,
0xae07a806,0xb02fa998,0xb2fdb103,0xb4d2b2f0,0xb56db478,0xb767b622,0xb745b65c,0xb8e1b84e,0xb880b813,0xb9e8b96a,0xb94bb8e8,0xbac1ba5b,0xba01b9a9,0xbb66bb1b,0xba9fba53,0xbbd1bba3,
0xae52a839,0xb055a9ca,0xb352b141,0xb4fcb32e,0xb5aeb4ae,0xb7a4b656,0xb799b6a7,0xb906b871,0xb8b1b841,0xba10b991,0xb981b91c,0xbae7ba82,0xba38b9e0,0xbb85bb3d,0xbad4ba8a,0xbbe3bbbc,
0xae9da86b,0xb07aa9fd,0xb3a8b17f,0xb526b36b,0xb5eeb4e4,0xb7e0b68a,0xb7ebb6f1,0xb92ab892,0xb8e1b86e,0xba36b9b7,0xb9b4b94e,0xbb0abaa8,0xba6cba14,0xbba0bb5d,0xbb04babc,0xbbf1bbd1,
0xaee8a89d,0xb09faa2f,0xb3fdb1bd,0xb54fb3a8,0xb62eb51a,0xb80eb6be,0xb81eb73a,0xb94eb8b4,0xb910b89a,0xba5bb9db,0xb9e6b97e,0xbb2cbacb,0xba9dba46,0xbbb8bb7b,0xbb31baec,0xbbfbbbe3,
0xb0c5aa61,0xb1eeabf2,0xb579b3e5,0xb6beb4e4,0xb82cb6f1,0xb90db83e,0xb971b8d4,0xba6cb9c8,0xba7fb9ff,0xbb66baf7,0xbb4bbaed,0xbbebbbb8,0xbbcdbb95,0xbbf4bc00,0xbbffbbf0,0xbb80bbca,
0xb0eaaa93,0xb213ac12,0xb5a2b411,0xb6e5b502,0xb849b724,0xb928b856,0xb993b8f5,0xba88b9e4,0xbaa1ba22,0xbb7cbb10,0xbb67bb0d,0xbbf4bbc8,0xbbdebbad,0xbbeabc00,0xbbffbbf9,0xbb5cbbb3,
0xb10faac5,0xb238ac2b,0xb5cbb42f,0xb70db520,0xb866b756,0xb942b86e,0xb9b4b914,0xbaa2b9ff,0xbac1ba44,0xbb90bb29,0xbb81bb2c,0xbbfbbbd6,0xbbebbbc1,0xbbdbbbfc,0xbbfbbbff,0xbb34bb98,
0xb134aaf8,0xb25dac44,0xb5f4b44e,0xb734b53d,0xb883b788,0xb95cb885,0xb9d5b934,0xbabcba1a,0xbae1ba65,0xbba3bb40,0xbb99bb48,0xbbffbbe3,0xbbf6bbd3,0xbbcabbf6,0xbbf2bc00,0xbb07bb7a,
0xb15aab2a,0xb282ac5e,0xb61db46c,0xb75cb55b,0xb89fb7ba,0xb975b89d,0xb9f5b953,0xbad5ba34,0xbafeba84,0xbbb4bb56,0xbbafbb62,0xbc00bbed,0xbbfcbbe2,0xbbb5bbed,0xbbe4bbfd,0xbad7bb57,
0xb17fab5c,0xb2a7ac77,0xb645b48a,0xb783b579,0xb8bbb7eb,0xb98eb8b4,0xba14b971,0xbaedba4e,0xbb1bbaa2,0xbbc3bb6b,0xbbc1bb7b,0xbbffbbf5,0xbc00bbee,0xbb9cbbe1,0xbbd2bbf6,0xbaa2bb31,
0xb1a4ab8e,0xb2ccac90,0xb66db4a8,0xb7a9b596,0xb8d7b80e,0xb9a7b8ca,0xba32b98e,0xbb04ba66,0xbb35bac0,0xbbd1bb7e,0xbbd2bb91,0xbbfbbbfb,0xbbffbbf7,0xbb80bbd2,0xbbbbbbeb,0xba6abb07,
0xb1c9abc0,0xb2f0aca9,0xb696b4c6,0xb7d0b5b3,0xb8f2b826,0xb9bfb8e1,0xba4fb9ab,0xbb1bba7f,0xbb4ebadc,0xbbddbb90,0xbbe0bba6,0xbbf5bbfe,0xbbfcbbfd,0xbb61bbc0,0xbba0bbdd,0xba2ebada,
0xb315acc2,0xb41dad8a,0xb7f6b5d1,0xb890b6b8,0xb9d7b8f7,0xba86b9a0,0xbb30ba96,0xbbb5bb39,0xbbe7bba1,0xbbfabbf6,0xbbecbc00,0xbb4cbbc1,0xbb3fbbab,0xb9bfba9f,0xb9efbaa9,0xb707b8b4,
0xb33aacdb,0xb42fada3,0xb80eb5ee,0xb8a2b6d4,0xb9efb90d,0xba9ab9b4,0xbb44baad,0xbbc1bb4b,0xbbefbbb0,0xbbf5bbfb,0xbbe0bbff,0xbb2dbbaf,0xbb19bb93,0xb983ba72,0xb9abba75,0xb656b869,
0xb35facf4,0xb441adbc,0xb821b60b,0xb8b4b6f1,0xba05b923,0xbaadb9c8,0xbb57bac3,0xbbcdbb5b,0xbbf6bbbe,0xbbeebbfe,0xbbd3bbfd,0xbb0cbb9c,0xbaf0bb78,0xb944ba42,0xb965ba3e,0xb5a2b81c,
0xb383ad0d,0xb454add5,0xb834b628,0xb8c5b70d,0xba1cb939,0xbac0b9db,0xbb69bad9,0xbbd6bb6b,0xbbfbbbcb,0xbbe5bc00,0xbbc2bbf8,0xbae9bb87,0xbac5bb5b,0xb903ba10,0xb91cba03,0xb4eab799,
0xb3a8ad26,0xb466adee,0xb846b645,0xb8d7b729,0xba32b94e,0xbad2b9ef,0xbb7bbaed,0xbbdfbb7a,0xbbfebbd6,0xbbdabc00,0xbbafbbf1,0xbac3bb6f,0xba96bb3b,0xb8c0b9db,0xb8cfb9c6,0xb42fb6f6,
0xb3cdad3f,0xb478ae07,0xb859b662,0xb8e8b745,0xba48b963,0xbae4ba01,0xbb8bbb01,0xbbe7bb88,0xbc00bbe0,0xbbcebbff,0xbb9abbe8,0xba9bbb56,0xba65bb18,0xb87bb9a5,0xb880b985,0xb2e4b651,
0xb3f1ad58,0xb48aae20,0xb86bb67f,0xb8fab761,0xba5db978,0xbaf5ba14,0xbb9abb15,0xbbeebb95,0xbc00bbe9,0xbbc0bbfc,0xbb82bbdd,0xba72bb3b,0xba30baf2,0xb834b96c,0xb82eb942,0xb166b5a8,
0xb40bad71,0xb49cae39,0xb87eb69b,0xb90bb77d,0xba72b98c,0xbb06ba26,0xbba8bb27,0xbbf4bba2,0xbbfebbf0,0xbbb0bbf9,0xbb68bbd0,0xba46bb1d,0xb9f9baca,0xb7d5b931,0xb7b4b8fc,0xafc9b4fc,
0x39b839ba,0x3a973ab5,0x39b339b5,0x3a583a78,0x39af39b1,0x3a153a37,0x39aa39ad,0x39cd39f2,0x39a639a8,0x398239a8,0x39a139a4,0x3933395b,0x399d399f,0x38e03909,0x3999399b,0x388938b5,
0xb979b972,0xb865b832,0xb986b980,0xb8c7b896,0xb994b98d,0xb924b8f6,0xb9a1b99b,0xb97db951,0xb9afb9a8,0xb9d2b9a8,0xb9bcb9b5,0xba21b9fa,0xb9c9b9c3,0xba6bba47,0xb9d6b9d0,0xbab0ba8e,
0xb9f4b9fe,0xbac7bae9,0xb9dfb9e9,0xba7ebaa3,0xb9c9b9d4,0xba2dba56,0xb9b3b9be,0xb9d6ba02,0xb99db9a8,0xb979b9a8,0xb986b992,0xb916b948,0xb970b97b,0xb8adb8e2,0xb958b964,0xb840b877,
0x39373927,0x381a37b7,0x39583948,0x38943858,0x39793969,0x390738ce,0x39993989,0x3974393e,0x39b839a8,0x39da39a8,0x39d639c7,0x3a393a0b,0x39f439e5,0x3a903a65,0x3a113a02,0x3ade3ab8,
0x3a2d3a3f,0x3af43b1a,0x3a093a1b,0x3aa23acc,0x39e339f6,0x3a453a74,0x39bc39d0,0x39df3a13,0x399439a8,0x397039a8,0x396b3980,0x38f83935,0x39413956,0x387a38ba,0x3916392b,0x37e83838,
0xb8f3b8d8,0xb79bb705,0xb929b90e,0xb85fb817,0xb95db943,0xb8eab8a6,0xb990b976,0xb96bb92b,0xb9c0b9a8,0xb9e3b9a8,0xb9f0b9d8,0xba50ba1b,0xba1dba07,0xbab3ba83,0xba49ba33,0xbb0abae0,
0xba64ba7c,0xbb1ebb46,0xba31ba4b,0xbac4baf3,0xb9fcba17,0xba5cba92,0xb9c5b9e1,0xb9e7ba23,0xb98bb9a8,0xb966b9a8,0xb94fb96d,0xb8dbb922,0xb911b930,0xb845b891,0xb8d1b8f1,0xb74eb7ee,
0x38ad3887,0x36ff364e,0x38f838d3,0x382a37ac,0x3941391d,0x38cc387c,0x39863964,0x39623918,0x39c939a8,0x39eb39a8,0x3a0939e9,0x3a673a2b,0x3a453a27,0x3ad53aa0,0x3a7e3a62,0x3b323b05,
0x3b453b6e,0x3bbc3bdd,0x3ae53b17,0x3b573b8f,0x3a733aae,0x3ac73b14,0x39f03a33,0x3a113a71,0x395d39a8,0x393739a8,0x38bc390e,0x384038bf,0x380f3867,0x365f3775,0x36af376a,0x341a3540,
0xb65fb593,0xb389b115,0xb7e8b726,0xb625b4f9,0xb8adb852,0xb830b748,0xb958b905,0xb933b8b5,0xb9f4b9a8,0xba15b9a8,0xba7eba3b,0xbad1ba78,0xbaf4babc,0xbb63bb20,0xbb57bb28,0xbbc6bb9b,
0xbb68bb91,0xbbd0bbed,0xbb04bb39,0xbb6fbba6,0xba89bac9,0xbadbbb2b,0xb9f8ba43,0xba19ba7f,0xb954b9a8,0xb92eb9a8,0xb89eb8fb,0xb820b8ab,0xb7b2b83d,0xb5ebb71b,0xb60eb6e3,0xb2deb4b1,
0x35bc34d5,0x32322f0e,0x377a369e,0x35b13469,0x388e3828,0x380f36ee,0x394f38f1,0x392938a0,0x39fc39a8,0x3a1d39a8,0x3a933a4b,0x3ae53a87,0x3b133ad6,0x3b7a3b36,0x3b783b49,0x3bd93bb1,
0x3b873baf,0x3be13bf8,0x3b213b58,0x3b853bbb,0x3a9e3ae3,0x3aee3b41,0x3a003a52,0x3a213a8e,0x394a39a8,0x392439a8,0x387f38e7,0x37fe3896,0x37423812,0x357636c1,0x356a3659,0x31853420,
0xb517b414,0xb0d7abd9,0xb70ab614,0xb53ab3ae,0xb86fb7f9,0xb7ddb693,0xb946b8dd,0xb91fb88c,0xba04b9a8,0xba25b9a8,0xbaa9ba5a,0xbaf7ba95,0xbb2fbaf0,0xbb90bb4b,0xbb96bb67,0xbbe8bbc4,
0xbba3bbc9,0xbbefbbff,0xbb3dbb74,0xbb9abbcd,0xbab3bafc,0xbb01bb55,0xba09ba62,0xba29ba9c,0xb941b9a8,0xb91bb9a8,0xb85fb8d3,0xb7bdb881,0xb6d2b7cd,0xb4ffb665,0xb4c3b5ce,0xb029b31b,
0x346f32a1,0x2ef52248,0x36993587,0x34c33288,0x385037a1,0x379b3637,0x393c38c9,0x39163877,0x3a0d39a8,0x3a2d39a8,0x3abd3a69,0x3b0a3aa3,0x3b4a3b08,0x3ba33b5f,0x3bb03b82,0x3bf43bd5,
0x3bf83c00,0x3bf93bd4,0x3bac3bdc,0x3be43bfe,0x3b133b69,0x3b543bab,0x3a313aaa,0x3a503ae0,0x391139a8,0x38ea39a8,0x377a386d,0x366b3817,0x34873608,0x313b348d,0x2d9731f4,0xad65291b,
0xac3828b6,0x2ec33365,0xb44bb160,0xb0bea57f,0xb759b5da,0xb648b45d,0xb90cb862,0xb8e5b80d,0xba35b9a8,0xba54b9a8,0xbb1bbab1,0xbb5cbae6,0xbbb5bb72,0xbbe9bbb2,0xbbfcbbe3,0xbbf5bc00,
0xbbfebbfc,0xbbefbbbc,0xbbbdbbe9,0xbbeebc00,0xbb24bb7b,0xbb63bbb9,0xba39bab8,0xba58baed,0xb907b9a8,0xb8e0b9a8,0xb737b858,0xb625b802,0xb40eb5ab,0xb042b42c,0xa9b1b0cb,0x30109a48,
0x25e4ad7e,0xb0beb475,0x33a23036,0x2f8ba3db,0x3715357c,0x360233f7,0x3902384d,0x38db37ee,0x3a3d39a8,0x3a5c39a8,0x3b2c3abf,0x3b6a3af3,0x3bc53b84,0x3bf23bc0,0x3bff3bee,0x3be93c00,
0x3c003bf4,0x3be23ba0,0x3bcc3bf3,0x3bf53bff,0x3b353b8c,0x3b713bc6,0x3a413ac6,0x3a603af9,0x38fd39a8,0x38d639a8,0x36f43842,0x35df37d8,0x3328354c,0x2e913396,0x16482f40,0xb16ca852,
0x251b304e,0x32193534,0xb2adae14,0xad972aac,0xb6d2b51d,0xb5bcb334,0xb8f8b838,0xb8d1b7c2,0xba45b9a8,0xba64b9a8,0xbb3dbacc,0xbb78baff,0xbbd3bb95,0xbbf8bbcb,0xbc00bbf7,0xbbdabbfd,
0xbbfebbe6,0xbbd2bb80,0xbbd9bbfa,0xbbfbbbfb,0xbb45bb9d,0xbb7fbbd1,0xba49bad3,0xba67bb05,0xb8f3b9a8,0xb8ccb9a8,0xb6afb82d,0xb599b7ac,0xb232b4ed,0xac9cb2d2,0x294dace7,0x32c62c83,
0xac06b1db,0xb371b5f1,0x31b62b75,0x2b43adb0,0x368d34bd,0x3576326f,0x38ee3822,0x38c73796,0x3a4d39a8,0x3a6b39a8,0x3b4c3ad9,0x3b853b0b,0x3bdf3ba4,0x3bfd3bd6,0x3bfc3bfd,0x3bc83bf8,
0x3bbd3b5a,0x3b473a99,0x3bfe3bf4,0x3bf93bbe,0x3b8b3bdb,0x3bb83bf7,0x3a6f3b11,0x3a8c3b3e,0x38c139a8,0x389939a8,0x35523780,0x343236cc,0x294d320d,0xad332de2,0xb40eaedc,0xb6a4b408,
0x346336aa,0x36f438b0,0xa6ad3004,0x2e2d3451,0xb52fb1aa,0xb40ead1a,0xb8bcb76a,0xb894b6b5,0xba73b9a8,0xba90b9a8,0xbb92bb17,0xbbbdbb43,0xbbffbbe0,0xbbf6bbf9,0xbbb2bbf0,0xbb35bbb4,
0xbba5bb30,0xbb21ba5e,0xbc00bbeb,0xbbf3bbaa,0xbb98bbe4,0xbbc2bbfb,0xba76bb1d,0xba93bb49,0xb8b7b9a8,0xb88eb9a8,0xb50bb753,0xb3d3b69e,0xa17fb147,0x2f27ac51,0x34b73099,0x37423499,
0xb50bb75e,0xb790b900,0x9cb6b12e,0xb010b4e1,0x34e730e4,0x33892b11,0x38b2373d,0x38893687,0x3a7a39a8,0x3a9739a8,0x3b9e3b22,0x3bc63b4e,0x3c003be8,0x3bef3bfd,0x3b983be5,0x3b0d3b9e,
0x3b893b02,0x3af73a1f,0x3c003bdf,0x3beb3b93,0x3ba33bec,0x3bcb3bfe,0x3a7e3b28,0x3a9b3b53,0x38ad39a8,0x388439a8,0x34c33726,0x33403670,0xa51b3080,0xb08d297f,0xb55eb1c3,0xb7ddb529,
0x35b13807,0x3815394d,0x28843257,0x31093570,0xb49fb01d,0xb2f7a7da,0xb8a8b710,0xb87fb659,0xba81b9a8,0xba9eb9a8,0xbba9bb2e,0xbbcfbb58,0xbbffbbef,0xbbe6bbff,0xbb7abbd7,0xbae1bb86,
0xbb6abad0,0xbacbb9dc,0xbbfdbbd0,0xbbe1bb79,0xbbaebbf2,0xbbd3bc00,0xba85bb33,0xbaa2bb5d,0xb8a3b9a8,0xb87ab9a8,0xb47bb6f9,0xb2adb642,0x2a7aaf72,0x3185a4b6,0x360232ea,0x383a35b6,
0xb654b85d,0xb85fb996,0xac38b37d,0xb201b5fd,0x34572eaa,0x32631e48,0x389e36e3,0x3874362b,0x3a8939a8,0x3aa539a8,0x3bb33b39,0x3bd73b62,0x3bfc3bf5,0x3bdc3c00,0x3b593bc7,0x3ab33b6b,
0x39b739b9,0x3a883aa6,0x39b239b4,0x3a483a68,0x39ae39b0,0x3a033a26,0x39a939ab,0x39bb39e0,0x39a539a7,0x396e3995,0x39a039a3,0x391e3947,0x399c399e,0x38ca38f5,0x3997399a,0x3873389f,
0xb97cb975,0xb87eb84c,0xb98ab983,0xb8deb8ae,0xb997b991,0xb93bb90d,0xb9a5b99e,0xb993b967,0xb9b2b9ab,0xb9e6b9bd,0xb9bfb9b9,0xba34ba0e,0xb9ccb9c6,0xba7dba59,0xb9d9b9d3,0xbac0ba9f,
0xb9efb9f9,0xbab6bad9,0xb9d9b9e4,0xba6aba91,0xb9c4b9cf,0xba18ba42,0xb9aeb9b9,0xb9bfb9ec,0xb997b9a3,0xb961b991,0xb981b98c,0xb8fcb92f,0xb96ab975,0xb892b8c8,0xb953b95e,0xb824b85c,
0x3940392f,0x383937f6,0x39613950,0x38b13876,0x39813971,0x392338eb,0x39a03991,0x398e395a,0x39bf39b0,0x39f339c1,0x39de39cf,0x3a4f3a22,0x39fb39ec,0x3aa43a7b,0x3a183a0a,0x3af03acb,
0x3a243a36,0x3ae13b07,0x39ff3a12,0x3a8b3ab7,0x39d939ec,0x3a2c3a5d,0x39b239c6,0x39c439f9,0x398a399e,0x3953398c,0x39613975,0x38d93917,0x3936394b,0x3859389a,0x390b3921,0x37a43816,
0xb901b8e6,0xb7e6b750,0xb936b91c,0xb883b83c,0xb96ab950,0xb90bb8c8,0xb99cb983,0xb98ab94b,0xb9ccb9b4,0xb9ffb9c6,0xb9fbb9e4,0xba6aba36,0xba28ba12,0xbacaba9b,0xba53ba3e,0xbb1dbaf5,
0xba57ba70,0xbb09bb33,0xba24ba3e,0xbaabbadc,0xb9efba0a,0xba40ba77,0xb9b7b9d3,0xb9c8ba05,0xb97cb99a,0xb944b988,0xb940b95e,0xb8b6b8fe,0xb901b921,0xb81eb86b,0xb8c0b8e1,0xb6fcb79e,
0x38c0389a,0x375636a7,0x390b38e6,0x38543800,0x3953392f,0x38f238a4,0x39973975,0x3985393d,0x39d939b9,0x3a0c39ca,0x3a1839f9,0x3a843a4a,0x3a533a36,0x3aed3abb,0x3a8b3a70,0x3b473b1c,
0x3b2e3b5a,0x3ba63bce,0x3aca3afe,0x3b373b74,0x3a533a91,0x3a9d3aef,0x39cc3a12,0x39de3a42,0x39363983,0x38fc3971,0x389238e6,0x37fb3880,0x37c5383c,0x35d136eb,0x3651370d,0x330934ae,
0xb6c3b5fa,0xb460b251,0xb824b788,0xb6b8b590,0xb8d9b880,0xb873b7d5,0xb981b92f,0xb96eb8f5,0xba18b9cf,0xba48b9e0,0xba9dba5d,0xbafabaa6,0xbb0fbad9,0xbb80bb43,0xbb6cbb40,0xbbd8bbb2,
0xbb51bb7d,0xbbbdbbe0,0xbae7bb1f,0xbb4ebb8c,0xba66baa9,0xbaafbb04,0xb9d1ba1e,0xb9e2ba4e,0xb928b97e,0xb8edb96c,0xb86eb8cd,0xb7afb866,0xb74bb80b,0xb54fb684,0xb5a2b679,0xb197b411,
0x362e3549,0x338330de,0x37e6370d,0x3651350e,0x38c0385c,0x38593788,0x397c3921,0x396a38e6,0x3a2439d3,0x3a5339e4,0x3ab63a70,0x3b0f3ab7,0x3b2e3af5,0x3b973b5a,0x3b8d3b61,0x3be83bc7,
0x3b703b9c,0x3bd03bef,0x3b033b3d,0x3b653ba2,0x3a793ac1,0x3ac03b19,0x39d53a2a,0x39e63a59,0x3919397a,0x38de3967,0x384938b4,0x3761384c,0x36cf37b4,0x34cc361d,0x34f035e2,0x302332e4,
0xb596b496,0xb244aecf,0xb783b690,0xb5e8b48a,0xb8a7b836,0xb83eb73a,0xb978b912,0xb965b8d7,0xba30b9d7,0xba5fb9e8,0xbacdba82,0xbb23bac8,0xbb4cbb10,0xbbacbb6f,0xbbaabb7f,0xbbf4bbd8,
0xbb8dbbb7,0xbbe0bbf9,0xbb1dbb5a,0xbb7abbb5,0xba8bbad9,0xbad0bb2d,0xb9d9ba36,0xb9eaba65,0xb90bb975,0xb8cfb963,0xb824b89a,0xb713b831,0xb651b750,0xb447b5b3,0xb43bb549,0xad58b1a4,
0x34fc33c0,0x31032bc0,0x371e3611,0x357e3405,0x388d3811,0x382436eb,0x39733903,0x396138c8,0x3a3c39db,0x3a6a39ec,0x3ae43a94,0x3b373ad9,0x3b673b2a,0x3bbe3b83,0x3bc33b9a,0x3bfc3be7,
0x3bed3bff,0x3bff3bea,0x3b8d3bc7,0x3bcc3bf5,0x3ae13b40,0x3b1d3b83,0x39ef3a70,0x39ff3a9b,0x38c0395e,0x3883394b,0x36c33816,0x357e3750,0x33833549,0x2e84332e,0x28cf3061,0xb0aca5b2,
0xaf7ea376,0x29663166,0xb514b2fd,0xb2bfad71,0xb809b69b,0xb734b555,0xb95cb8b9,0xb949b87b,0xba75b9f1,0xbaa1ba01,0xbb49bae9,0xbb8bbb25,0xbbcfbb96,0xbbf9bbd2,0xbc00bbf2,0xbbe3bbfe,
0xbbf6bc00,0xbbfcbbda,0xbb9fbbd6,0xbbd8bbfb,0xbaf0bb52,0xbb2cbb92,0xb9f3ba7b,0xba03baa6,0xb8b1b95a,0xb873b947,0xb673b7f6,0xb52cb718,0xb276b4de,0xac5eb251,0x2052ae39,0x321f2bf2,
0x2cf4a806,0xad3fb2d8,0x34a831ee,0x31e22a93,0x37db364b,0x36fc3502,0x395738a9,0x3944386b,0x3a8039f5,0x3aab3a05,0x3b5b3af8,0x3b993b33,0x3bdd3ba7,0x3bfd3bdd,0x3bff3bfa,0x3bd13bf9,
0x3bfd3bfd,0x3bf53bc6,0x3baf3be3,0x3be23bff,0x3b003b64,0x3b393ba0,0x39f73a86,0x3a083ab0,0x38a23955,0x38633942,0x362237bf,0x34d836e0,0x31663472,0x286b3172,0xaaf82b5c,0xb390ae84,
0xa8cf2cf4,0x2fc93423,0xb43bb0de,0xb103a484,0xb7a4b5fa,0xb6c3b4ae,0xb953b89a,0xb940b85c,0xba8bb9f9,0xbab6ba0a,0xbb6cbb07,0xbba6bb40,0xbbe8bbb7,0xbc00bbe7,0xbbfabbff,0xbbbabbf1,
0xbc00bbf6,0xbbebbbae,0xbbbebbed,0xbbebbc00,0xbb0fbb74,0xbb47bbad,0xb9fbba91,0xba0cbabb,0xb892b950,0xb854b93d,0xb5d1b788,0xb484b6a7,0xb055b405,0x9248b093,0x2e6ba484,0x347e3086,
0x98b6afe2,0xb128b4d8,0x339c2f97,0x3023a420,0x376c35a8,0x368a345a,0x394e388b,0x393b384c,0x3a9639fd,0x3ac03a0e,0x3b7c3b16,0x3bb33b4d,0x3bf23bc5,0x3c003bef,0x3bf03c00,0x3ba03be5,
0x3bde3b91,0x3b8a3af7,0x3bf23bff,0x3c003be3,0x3b533bb9,0x3b823bdf,0x3a103ac5,0x3a203aec,0x38443939,0x38033925,0x342f366d,0x31b03584,0xa8392f65,0xb15a1d7f,0xb531b1c9,0xb7e0b55b,
0x3269358a,0x35a83819,0xae842a61,0x205231e2,0xb651b405,0xb567b15a,0xb936b83c,0xb923b7f6,0xbacaba12,0xbaf0ba22,0xbbbebb5a,0xbbe3bb88,0xbbfdbbf5,0xbbddbc00,0xbb81bbd6,0xbadfbb7c,
0xbbcebb70,0xbb6dbac6,0xbbf8bbfb,0xbbffbbd6,0xbb60bbc4,0xbb8dbbe7,0xba14bacf,0xba24baf5,0xb834b934,0xb7e6b921,0xb3b4b634,0xb103b549,0x2c44ada3,0x326925b2,0x35e23309,0x384135f4,
0xb3a8b63a,0xb63fb869,0x2cc2ad58,0xa89db2f0,0x3617335f,0x352c30ac,0x3931382c,0x391e37d5,0x3ad43a16,0x3afa3a26,0x3bc93b66,0x3bea3b92,0x3bf93bfa,0x3bcf3bff,0x3b5f3bc5,0x3aad3b5d,
0x3bba3b4c,0x3b4d3a93,0x3bfc3bf6,0x3bfd3bc7,0x3b6c3bce,0x3b973bed,0x3a183ad9,0x3a283afe,0x3824392f,0x37c5391c,0x330935fa,0x3055350e,0xae6b2bc0,0xb377aa61,0xb690b423,0xb890b68a,
0x347236e5,0x36d438b6,0xa9fd2f7e,0x2c1233fd,0xb5dcb2b3,0xb4f0affb,0xb92db81c,0xb919b7b4,0xbaddba1a,0xbb03ba2a,0xbbd3bb72,0xbbf0bb9c,0xbbf2bbfe,0xbbbfbbfc,0xbb38bbaf,0xba77bb3c,
0xbba4bb23,0xbb2aba5b,0xbbffbbee,0xbbfabbb6,0xbb77bbd7,0xbba1bbf3,0xba1cbae2,0xba2cbb07,0xb813b92a,0xb7a4b917,0xb25db5bf,0xaf4cb4d2,0x3048a839,0x34412cf4,0x373a34c0,0x38dc371e,
0xb50eb78e,0xb767b901,0x24e9b0d1,0xadd5b484,0x35a23207,0x34b42e9d,0x3928380b,0x39143793,0x3ae73a1e,0x3b0c3a2e,0x3bdb3b7d,0x3bf53ba6,0x3be93c00,0x3bad3bf7,0x3b0d3b97,0x3a3e3b18,
0xb999b996,0xb889b85d,0xb99db99b,0xb8e0b8b5,0xb9a1b99f,0xb933b909,0xb9a6b9a4,0xb982b95b,0xb9aab9a8,0xb9cdb9a8,0xb9afb9ad,0xba15b9f2,0xb9b3b9b1,0xba58ba37,0xb9b8b9b5,0xba97ba78,
0xb9d6b9dc,0xbab0bad0,0xb9c9b9d0,0xba6bba8e,0xb9bcb9c3,0xba21ba47,0xb9afb9b5,0xb9d2b9fa,0xb9a1b9a8,0xb97db9a8,0xb994b99b,0xb924b951,0xb986b98d,0xb8c7b8f6,0xb979b980,0xb865b896,
0x3958394d,0x38403807,0x39703964,0x38ad3877,0x3986397b,0x391638e2,0x399d3992,0x39793948,0x39b339a8,0x39d639a8,0x39c939be,0x3a2d3a02,0x39df39d4,0x3a7e3a56,0x39f439e9,0x3ac73aa3,
0x3a113a1f,0x3ade3b02,0x39f43a02,0x3a903ab8,0x39d639e5,0x3a393a65,0x39b839c7,0x39da3a0b,0x399939a8,0x397439a8,0x39793989,0x3907393e,0x39583969,0x389438ce,0x39373948,0x381a3858,
0xb916b900,0xb7e8b75e,0xb941b92b,0xb87ab838,0xb96bb956,0xb8f8b8ba,0xb994b980,0xb970b935,0xb9bcb9a8,0xb9dfb9a8,0xb9e3b9d0,0xba45ba13,0xba09b9f6,0xbaa2ba74,0xba2dba1b,0xbaf4bacc,
0xba49ba5e,0xbb0abb30,0xba1dba33,0xbab3bae0,0xb9f0ba07,0xba50ba83,0xb9c0b9d8,0xb9e3ba1b,0xb990b9a8,0xb96bb9a8,0xb95db976,0xb8eab92b,0xb929b943,0xb85fb8a6,0xb8f3b90e,0xb79bb817,
0x38d138b0,0x374e36aa,0x391138f1,0x384537ee,0x394f3930,0x38db3891,0x398b396d,0x39663922,0x39c539a8,0x39e739a8,0x39fc39e1,0x3a5c3a23,0x3a313a17,0x3ac43a92,0x3a643a4b,0x3b1e3af3,
0x3a7e3a99,0x3b323b5a,0x3a453a62,0x3ad53b05,0x3a093a27,0x3a673aa0,0x39c939e9,0x39eb3a2b,0x398639a8,0x396239a8,0x39413964,0x38cc3918,0x38f8391d,0x382a387c,0x38ad38d3,0x36ff37ac,
0xb6afb5f1,0xb41ab1db,0xb80fb76a,0xb65fb540,0xb8bcb867,0xb840b775,0xb95db90e,0xb937b8bf,0xb9f0b9a8,0xba11b9a8,0xba73ba33,0xbac7ba71,0xbae5baae,0xbb57bb14,0xbb45bb17,0xbbbcbb8f,
0xbb57bb80,0xbbc6bbe6,0xbaf4bb28,0xbb63bb9b,0xba7ebabc,0xbad1bb20,0xb9f4ba3b,0xba15ba78,0xb958b9a8,0xb933b9a8,0xb8adb905,0xb830b8b5,0xb7e8b852,0xb625b748,0xb65fb726,0xb389b4f9,
0x360e3534,0x32de304e,0x37b236e3,0x35eb34b1,0x389e383d,0x3820371b,0x395438fb,0x392e38ab,0x39f839a8,0x3a1939a8,0x3a893a43,0x3adb3a7f,0x3b043ac9,0x3b6f3b2b,0x3b683b39,0x3bd03ba6,
0x3b783ba0,0x3bd93bf4,0x3b133b49,0x3b7a3bb1,0x3a933ad6,0x3ae53b36,0x39fc3a4b,0x3a1d3a87,0x394f39a8,0x392939a8,0x388e38f1,0x380f38a0,0x377a3828,0x35b136ee,0x35bc369e,0x32323469,
0xb56ab475,0xb185ad7e,0xb742b659,0xb576b420,0xb87fb812,0xb7feb6c1,0xb94ab8e7,0xb924b896,0xba00b9a8,0xba21b9a8,0xba9eba52,0xbaeeba8e,0xbb21bae3,0xbb85bb41,0xbb87bb58,0xbbe1bbbb,
0xbb96bbbc,0xbbe8bbfc,0xbb2fbb67,0xbb90bbc4,0xbaa9baf0,0xbaf7bb4b,0xba04ba5a,0xba25ba95,0xb946b9a8,0xb91fb9a8,0xb86fb8dd,0xb7ddb88c,0xb70ab7f9,0xb53ab693,0xb517b614,0xb0d7b3ae,
0x34c33365,0x302928b6,0x36d235ce,0x34ff331b,0x385f37cd,0x37bd3665,0x394138d3,0x391b3881,0x3a0939a8,0x3a2939a8,0x3ab33a62,0x3b013a9c,0x3b3d3afc,0x3b9a3b55,0x3ba33b74,0x3bef3bcd,
0x3bb03bd4,0x3bf43c00,0x3b4a3b82,0x3ba33bd5,0x3abd3b08,0x3b0a3b5f,0x3a0d3a69,0x3a2d3aa3,0x393c39a8,0x391639a8,0x385038c9,0x379b3877,0x369937a1,0x34c33637,0x346f3587,0x2ef53288,
0xad972248,0x2d6532a1,0xb487b1f4,0xb13ba91b,0xb77ab608,0xb66bb48d,0xb911b86d,0xb8eab817,0xba31b9a8,0xba50b9a8,0xbb13baaa,0xbb54bae0,0xbbacbb69,0xbbe4bbab,0xbbf8bbdc,0xbbf9bbfe,
0xbbfcbbff,0xbbf5bbc9,0xbbb5bbe3,0xbbe9bc00,0xbb1bbb72,0xbb5cbbb2,0xba35bab1,0xba54bae6,0xb90cb9a8,0xb8e5b9a8,0xb759b862,0xb648b80d,0xb44bb5da,0xb0beb45d,0xac38b160,0x2ec3a57f,
0x29b1abd9,0xb010b414,0x340e30cb,0x30421a48,0x373735ab,0x3625342c,0x39073858,0x38e03802,0x3a3939a8,0x3a5839a8,0x3b243ab8,0x3b633aed,0x3bbd3b7b,0x3bee3bb9,0x3bfe3be9,0x3bef3c00,
0x3bff3bf8,0x3be93baf,0x3bc53bee,0x3bf23c00,0x3b2c3b84,0x3b6a3bc0,0x3a3d3abf,0x3a5c3af3,0x390239a8,0x38db39a8,0x3715384d,0x360237ee,0x33a2357c,0x2f8b33f7,0x25e43036,0xb0bea3db,
0x96482f0e,0x316c34d5,0xb328af40,0xae912852,0xb6f4b54c,0xb5dfb396,0xb8fdb842,0xb8d6b7d8,0xba41b9a8,0xba60b9a8,0xbb35bac6,0xbb71baf9,0xbbccbb8c,0xbbf5bbc6,0xbc00bbf3,0xbbe2bbff,
0xbc00bbed,0xbbdabb91,0xbbd3bbf7,0xbbf8bbfd,0xbb3dbb95,0xbb78bbcb,0xba45bacc,0xba64baff,0xb8f8b9a8,0xb8d1b9a8,0xb6d2b838,0xb5bcb7c2,0xb2adb51d,0xad97b334,0x251bae14,0x32192aac,
0xa94db115,0xb2c6b593,0x32322ce7,0x2c9cac83,0x36af34ed,0x359932d2,0x38f3382d,0x38cc37ac,0x3a4939a8,0x3a6739a8,0x3b453ad3,0x3b7f3b05,0x3bd93b9d,0x3bfb3bd1,0x3bfe3bfa,0x3bd23bfb,
0x3bfc3bdd,0x3bc83b6e,0x3bdf3bfd,0x3bfd3bf8,0x3b4c3ba4,0x3b853bd6,0x3a4d3ad9,0x3a6b3b0b,0x38ee39a8,0x38c739a8,0x368d3822,0x35763796,0x31b634bd,0x2b43326f,0xac062b75,0xb371adb0,
0x340e364e,0x36a43887,0xa94d2edc,0x2d333408,0xb552b20d,0xb432ade2,0xb8c1b780,0xb899b6cc,0xba6fb9a8,0xba8cb9a8,0xbb8bbb11,0xbbb8bb3e,0xbbfebbdb,0xbbf9bbf7,0xbbbdbbf4,0xbb47bbbe,
0xbbb2bb46,0xbb35ba7c,0xbbffbbf0,0xbbf6bbb4,0xbb92bbe0,0xbbbdbbf9,0xba73bb17,0xba90bb43,0xb8bcb9a8,0xb894b9a8,0xb52fb76a,0xb40eb6b5,0xa6adb1aa,0x2e2dad1a,0x34633004,0x36f43451,
0xb4b7b705,0xb742b8d8,0x217fb099,0xaf27b499,0x350b3147,0x33d32c51,0x38b73753,0x388e369e,0x3a7639a8,0x3a9339a8,0x3b983b1d,0x3bc23b49,0x3c003be4,0x3bf33bfb,0x3ba53beb,0x3b213baa,
0x3b983b1a,0x3b0d3a3f,0x3c003be5,0x3bef3b9e,0x3b9e3be8,0x3bc63bfd,0x3a7a3b22,0x3a973b4e,0x38b239a8,0x388939a8,0x34e7373d,0x33893687,0x9cb630e4,0xb0102b11,0xb50bb12e,0xb790b4e1,
0x355e37b7,0x37dd3927,0x251b31c3,0x308d3529,0xb4c3b080,0xb340a97f,0xb8adb726,0xb884b670,0xba7eb9a8,0xba9bb9a8,0xbba3bb28,0xbbcbbb53,0xbc00bbec,0xbbebbbfe,0xbb89bbdf,0xbaf7bb93,
0xbb7abae9,0xbae1b9fe,0xbbffbbd7,0xbbe6bb86,0xbba9bbef,0xbbcfbbff,0xba81bb2e,0xba9ebb58,0xb8a8b9a8,0xb87fb9a8,0xb49fb710,0xb2f7b659,0x2884b01d,0x3109a7da,0x35b13257,0x38153570,
0xb602b832,0xb83ab972,0xaa7ab2ea,0xb185b5b6,0x347b2f72,0x32ad24b6,0x38a336f9,0x387a3642,0x3a8539a8,0x3aa239a8,0x3bae3b33,0x3bd33b5d,0x3bfd3bf2,0x3be13c00,0x3b6a3bd0,0x3acb3b79,
0x3b593ab5,0x3ab339ba,0x3bfc3bc7,0x3bdc3b6b,0x3bb33bf5,0x3bd73c00,0x3a893b39,0x3aa53b62,0x389e39a8,0x387439a8,0x345736e3,0x3263362b,0xac382eaa,0xb2011e48,0xb654b37d,0xb85fb5fd,
0xb99ab997,0xb89fb873,0xb99eb99c,0xb8f5b8ca,0xb9a3b9a0,0xb947b91e,0xb9a7b9a5,0xb995b96e,0xb9abb9a9,0xb9e0b9bb,0xb9b0b9ae,0xba26ba03,0xb9b4b9b2,0xba68ba48,0xb9b9b9b7,0xbaa6ba88,
0xb9d3b9d9,0xba9fbac0,0xb9c6b9cc,0xba59ba7d,0xb9b9b9bf,0xba0eba34,0xb9abb9b2,0xb9bdb9e6,0xb99eb9a5,0xb967b993,0xb991b997,0xb90db93b,0xb983b98a,0xb8aeb8de,0xb975b97c,0xb84cb87e,
0x395e3953,0x385c3824,0x3975396a,0x38c83892,0x398c3981,0x392f38fc,0x39a33997,0x39913961,0x39b939ae,0x39ec39bf,0x39cf39c4,0x3a423a18,0x39e439d9,0x3a913a6a,0x39f939ef,0x3ad93ab6,
0x3a0a3a18,0x3acb3af0,0x39ec39fb,0x3a7b3aa4,0x39cf39de,0x3a223a4f,0x39b039bf,0x39c139f3,0x399139a0,0x395a398e,0x39713981,0x38eb3923,0x39503961,0x387638b1,0x392f3940,0x37f63839,
0xb921b90b,0xb816b7a4,0xb94bb936,0xb89ab859,0xb975b961,0xb917b8d9,0xb99eb98a,0xb98cb953,0xb9c6b9b2,0xb9f9b9c4,0xb9ecb9d9,0xba5dba2c,0xba12b9ff,0xbab7ba8b,0xba36ba24,0xbb07bae1,
0xba3eba53,0xbaf5bb1d,0xba12ba28,0xba9bbaca,0xb9e4b9fb,0xba36ba6a,0xb9b4b9cc,0xb9c6b9ff,0xb983b99c,0xb94bb98a,0xb950b96a,0xb8c8b90b,0xb91cb936,0xb83cb883,0xb8e6b901,0xb750b7e6,
0x38e138c0,0x379e36fc,0x39213901,0x386b381e,0x395e3940,0x38fe38b6,0x399a397c,0x39883944,0x39d339b7,0x3a0539c8,0x3a0a39ef,0x3a773a40,0x3a3e3a24,0x3adc3aab,0x3a703a57,0x3b333b09,
0x3a703a8b,0x3b1c3b47,0x3a363a53,0x3abb3aed,0x39f93a18,0x3a4a3a84,0x39b939d9,0x39ca3a0c,0x39753997,0x393d3985,0x392f3953,0x38a438f2,0x38e6390b,0x38003854,0x389a38c0,0x36a73756,
0xb70db651,0xb4aeb309,0xb83cb7c5,0xb6ebb5d1,0xb8e6b892,0xb880b7fb,0xb983b936,0xb971b8fc,0xba12b9cc,0xba42b9de,0xba91ba53,0xbaefba9d,0xbafebaca,0xbb74bb37,0xbb5abb2e,0xbbcebba6,
0xbb40bb6c,0xbbb2bbd8,0xbad9bb0f,0xbb43bb80,0xba5dba9d,0xbaa6bafa,0xb9cfba18,0xb9e0ba48,0xb92fb981,0xb8f5b96e,0xb880b8d9,0xb7d5b873,0xb788b824,0xb590b6b8,0xb5fab6c3,0xb251b460,
0x367935a2,0x34113197,0x380b374b,0x3684354f,0x38cd386e,0x386637af,0x397e3928,0x396c38ed,0x3a1e39d1,0x3a4e39e2,0x3aa93a66,0x3b043aaf,0x3b1f3ae7,0x3b8c3b4e,0x3b7d3b51,0x3be03bbd,
0x3b613b8d,0x3bc73be8,0x3af53b2e,0x3b5a3b97,0x3a703ab6,0x3ab73b0f,0x39d33a24,0x39e43a53,0x3921397c,0x38e6396a,0x385c38c0,0x37883859,0x370d37e6,0x350e3651,0x3549362e,0x30de3383,
0xb5e2b4f0,0xb2e4b023,0xb7b4b6cf,0xb61db4cc,0xb8b4b849,0xb84cb761,0xb97ab919,0xb967b8de,0xba2ab9d5,0xba59b9e6,0xbac1ba79,0xbb19bac0,0xbb3dbb03,0xbba2bb65,0xbb9cbb70,0xbbefbbd0,
0xbb7fbbaa,0xbbd8bbf4,0xbb10bb4c,0xbb6fbbac,0xba82bacd,0xbac8bb23,0xb9d7ba30,0xb9e8ba5f,0xb912b978,0xb8d7b965,0xb836b8a7,0xb73ab83e,0xb690b783,0xb48ab5e8,0xb496b596,0xaecfb244,
0x3549343b,0x31a42d58,0x37503651,0x35b33447,0x389a3824,0x38313713,0x3975390b,0x396338cf,0x3a3639d9,0x3a6539ea,0x3ad93a8b,0x3b2d3ad0,0x3b5a3b1d,0x3bb53b7a,0x3bb73b8d,0x3bf93be0,
0x3b9a3bc3,0x3be73bfc,0x3b2a3b67,0x3b833bbe,0x3a943ae4,0x3ad93b37,0x39db3a3c,0x39ec3a6a,0x39033973,0x38c83961,0x3811388d,0x36eb3824,0x3611371e,0x3405357e,0x33c034fc,0x2bc03103,
0xb061a8cf,0x25b230ac,0xb549b383,0xb32eae84,0xb816b6c3,0xb750b57e,0xb95eb8c0,0xb94bb883,0xba70b9ef,0xba9bb9ff,0xbb40bae1,0xbb83bb1d,0xbbc7bb8d,0xbbf5bbcc,0xbbffbbed,0xbbeabbff,
0xbbf2bc00,0xbbfebbe3,0xbb96bbcf,0xbbd2bbf9,0xbae9bb49,0xbb25bb8b,0xb9f1ba75,0xba01baa1,0xb8b9b95c,0xb87bb949,0xb69bb809,0xb555b734,0xb2fdb514,0xad71b2bf,0xa376af7e,0x31662966,
0x2e39a052,0xabf2b21f,0x34de3276,0x32512c5e,0x37f63673,0x3718352c,0x395a38b1,0x39473873,0x3a7b39f3,0x3aa63a03,0x3b523af0,0x3b923b2c,0x3bd63b9f,0x3bfb3bd8,0x3c003bf6,0x3bda3bfc,
0x3bfa3bff,0x3bf93bd1,0x3ba73bdd,0x3bdd3bfd,0x3af83b5b,0x3b333b99,0x39f53a80,0x3a053aab,0x38a93957,0x386b3944,0x364b37db,0x350236fc,0x31ee34a8,0x2a9331e2,0xa8062cf4,0xb2d8ad3f,
0xab5c2af8,0x2e843390,0xb472b166,0xb172a86b,0xb7bfb622,0xb6e0b4d8,0xb955b8a2,0xb942b863,0xba86b9f7,0xbab0ba08,0xbb64bb00,0xbba0bb39,0xbbe3bbaf,0xbbffbbe2,0xbbfdbbfd,0xbbc6bbf5,
0xbbffbbfa,0xbbf1bbba,0xbbb7bbe8,0xbbe7bc00,0xbb07bb6c,0xbb40bba6,0xb9f9ba8b,0xba0abab6,0xb89ab953,0xb85cb940,0xb5fab7a4,0xb4aeb6c3,0xb0deb43b,0xa484b103,0x2cf4a8cf,0x34232fc9,
0x2484ae6b,0xb086b47e,0x34053055,0x30931248,0x378835d1,0x36a73484,0x39503892,0x393d3854,0x3a9139fb,0x3abb3a0c,0x3b743b0f,0x3bad3b47,0x3bed3bbe,0x3c003beb,0x3bf63c00,0x3bae3beb,
0x3c003bf0,0x3be53ba0,0x3bc53bf2,0x3bef3c00,0x3b163b7c,0x3b4d3bb3,0x39fd3a96,0x3a0e3ac0,0x388b394e,0x384c393b,0x35a8376c,0x345a368a,0x2f97339c,0xa4203023,0xafe298b6,0xb4d8b128,
0x31c93531,0x355b37e0,0xaf652839,0x9d7f315a,0xb66db42f,0xb584b1b0,0xb939b844,0xb925b803,0xbac5ba10,0xbaecba20,0xbbb9bb53,0xbbdfbb82,0xbbffbbf2,0xbbe3bc00,0xbb91bbde,0xbaf7bb8a,
0xbbd6bb81,0xbb7cbadf,0xbbf5bbfd,0xbc00bbdd,0xbb5abbbe,0xbb88bbe3,0xba12baca,0xba22baf0,0xb83cb936,0xb7f6b923,0xb405b651,0xb15ab567,0x2a61ae84,0x31e22052,0x358a3269,0x381935a8,
0xb309b5e2,0xb5f4b841,0x2da3ac44,0xa5b2b269,0x363433b4,0x35493103,0x39343834,0x392137e6,0x3acf3a14,0x3af53a24,0x3bc43b60,0x3be73b8d,0x3bfb3bf8,0x3bd63bff,0x3b703bce,0x3ac63b6d,
0x3bc53b5f,0x3b5d3aad,0x3bfa3bf9,0x3bff3bcf,0x3b663bc9,0x3b923bea,0x3a163ad4,0x3a263afa,0x382c3931,0x37d5391e,0x335f3617,0x30ac352c,0xad582cc2,0xb2f0a89d,0xb63ab3a8,0xb869b63f,
0x34233690,0x368a3890,0xabc02e6b,0x2a613377,0xb5fab309,0xb50eb055,0xb92fb824,0xb91cb7c5,0xbad9ba18,0xbafeba28,0xbbcebb6c,0xbbedbb97,0xbbf6bbfc,0xbbc7bbfd,0xbb4cbbba,0xba93bb4d,
0xbbafbb38,0xbb3cba77,0xbbfebbf2,0xbbfcbbbf,0xbb72bbd3,0xbb9cbbf0,0xba1abadd,0xba2abb03,0xb81cb92d,0xb7b4b919,0xb2b3b5dc,0xaffbb4f0,0x2f7ea9fd,0x33fd2c12,0x36e53472,0x38b636d4,
0xb4c0b73a,0xb71eb8dc,0x2839b048,0xacf4b441,0x35bf325d,0x34d22f4c,0x392a3813,0x391737a4,0x3ae23a1c,0x3b073a2c,0x3bd73b77,0x3bf33ba1,0x3bee3bff,0x3bb63bfa,0x3b233ba4,0x3a5b3b2a,
0x3b973b0d,0x3b183a3e,0x3c003be9,0x3bf73bad,0x3b7d3bdb,0x3ba63bf5,0x3a1e3ae7,0x3a2e3b0c,0x380b3928,0x37933914,0x320735a2,0x2e9d34b4,0xb0d124e9,0xb484add5,0xb78eb50e,0xb901b767,
0xb97239ba,0x39dc3996,0xb8323ab5,0x3ad0385d,0x3927b9fe,0xba1fb94d,0x37b7bae9,0xbb02b807,0xb8d83a3f,0x3a5e3900,0xb7053b1a,0x3b30375e,0x3887ba7c,0xba99b8b0,0x364ebb46,0xbb5ab6aa,
0xb90039dc,0x3a3f3972,0xad7e3be6,0x3bf83115,0x3807ba99,0xbae9b887,0xabd9bc00,0xbbfca248,0xb5f13b30,0x3b6e3705,0x32a13bed,0x3bd4b04e,0x3365bba0,0xbbc9b4d5,0xb593bbaf,0xbb803475,
0xb88739fe,0x3a99394d,0x35f13bbc,0x3b6eb414,0x3593bb1a,0xbb80b75e,0xb8b0bb02,0xba7c37b7,0xaf0e3bc9,0x3bf43365,0x3a1f39dc,0x3927b972,0xb04ebc00,0xbbed2248,0xbb30b85d,0xb7053ab5,
0xb8073a1f,0x3ae93927,0x39fe3a3f,0x394db900,0x31dbbb80,0xbbddb593,0xbb6eb832,0xb5f13ad0,0x31153c00,0x3be62248,0x3bff32a1,0x28b6bbd4,0xb7b7bb91,0xbb023534,0xbba0304e,0x34d53bed,
0xb7053a3f,0x3b303900,0x3bbc375e,0x3414bb1a,0x2248bbc9,0xbc00b365,0xbbdda8b6,0x31db3bff,0x36aa3bd4,0x3b46b2a1,0x3a7cb64e,0xb8b0bb5a,0xba1fba5e,0xb92738d8,0xb7b739fe,0x3b02394d,
0xb5f13a5e,0x3b6e38d8,0x3bd42bd9,0xb2a1bbfc,0xb115bbf4,0xbbe6af0e,0xb9dc375e,0x39723b1a,0x39273b46,0x3a1fb6aa,0x3475bad0,0xbbafb832,0xbb91b887,0xb5343a99,0x34143c00,0x3bbc2248,
0xb4d53a7c,0x3ba038b0,0x3a3fb593,0xb900bb80,0xb534bc00,0xbb912248,0xb4143ab5,0x3bbc385d,0x3a993a5e,0x3887b8d8,0xb5f1bbfc,0xbb6e2bd9,0xbbffb475,0x28b63baf,0x3ad03a1f,0x3832b927,
0xb3653a99,0x3bc93887,0x36aab996,0xbb46b9ba,0xb7b7bbed,0xbb02304e,0x34d53bfc,0x3ba02bd9,0x3b913927,0x3534ba1f,0xbae9ba3f,0xb8073900,0xbb5a28b6,0x364e3bff,0x3bd43115,0xb2a1bbe6,
0xb1153ab5,0x3be6385d,0xa8b6bb6e,0xbbffb5f1,0xb900bbbc,0xba3f3414,0x3a1f3b30,0x3927b705,0x3bfc375e,0x2bd9bb1a,0xbbedb475,0x304e3baf,0xb9ba3593,0x39963b80,0x3887b832,0xba99bad0,
0xad7e3ad0,0x3bf83832,0xb7b7bbff,0xbb0228b6,0xb9febb6e,0xb94d35f1,0x3bed3887,0x304eba99,0x3bd43414,0xb2a1bbbc,0xb9963534,0x39ba3b91,0xb6aa3900,0x3b463a3f,0xb115bba0,0xbbe6b4d5,
0xa2483ae9,0x3c003807,0xba99bb30,0xb8873705,0xbad0bb02,0xb83237b7,0x3b462d7e,0xb6aabbf8,0x3b1a28b6,0xb75ebbff,0xaf0e3a7c,0x3bf438b0,0xabd93ab5,0x3bfc385d,0xba5ebb5a,0xb8d8364e,
0x2bd93b02,0x3bfc37b7,0xbbedb927,0xb04e3a1f,0xbb6eba7c,0xb5f138b0,0x385db6aa,0xbab5bb46,0x39dcb1db,0xb972bbdd,0x38323c00,0x3ad02248,0x34d53bbc,0x3ba03414,0xbbf4b705,0x2f0e3b30,
0x304e3b1a,0x3bed375e,0xbb91b475,0x35343baf,0xbbd4b9dc,0xb2a13972,0x2248ba7c,0xbc00b8b0,0x3832b64e,0xbad0bb5a,0x3b803a99,0x3593b887,0x39003bfc,0x3a3fabd9,0xb9273414,0x3a1f3bbc,
0x32a13b30,0x3bd43705,0xb996304e,0x39ba3bed,0xbbffb927,0xa8b63a1f,0xb832bbf4,0xbad0af0e,0x3475b8b0,0xbbafba7c,0x3ba03593,0xb4d5bb80,0x3ae93b6e,0x3807b5f1,0x2bd93a99,0x3bfc3887,
0x34753b46,0x3baf36aa,0xb4d53832,0x3ba03ad0,0xbbedb85d,0x304e3ab5,0xbb30bb5a,0xb705364e,0x2248b9fe,0xbc00b94d,0x3887b414,0xba99bbbc,0x3be63a1f,0x3115b927,0x39dc3bf4,0x3972af0e,
0x35933b5a,0x3b80364e,0x31153a99,0x3be63887,0xbba0b705,0x34d53b30,0xbbf4b8d8,0x2f0e3a5e,0xb414bb02,0xbbbcb7b7,0xabd9ba1f,0xbbfcb927,0x3bd43832,0xb2a1bad0,0x3c003972,0xa248b9dc,
0x36aa3b6e,0x3b4635f1,0x38b03bdd,0x3a7c31db,0xbb1ab534,0x375e3b91,0xba3fb04e,0x39003bed,0xb807bbaf,0xbae9b475,0xb94dbbf8,0xb9fead7e,0x3ab53365,0xb85dbbc9,0x39ba28b6,0xb996bbff,
0x37b73b80,0x3b023593,0x3b1a3bc9,0x375eb365,0xba5eb2a1,0x38d83bd4,0xb53435f1,0x3b913b6e,0xb9babbfc,0xb996abd9,0xbbddbae9,0xb1db3807,0x38b0ad7e,0xba7cbbf8,0x28b6b900,0xbbffba3f,
0x385d3b91,0x3ab53534,0x3c003a5e,0x2248b8d8,0xb972ad7e,0x39dc3bf8,0x33653a3f,0x3bc93900,0xbb02bbe6,0xb7b73115,0xbb1ab6aa,0x375e3b46,0x3414b64e,0xbbbcbb5a,0xb94dbbdd,0xb9feb1db,
0x38d83ba0,0x3a5e34d5,0x3b3037b7,0xb705bb02,0xb85d28b6,0x3ab53bff,0x39ba3be6,0x39963115,0xbbc9bb6e,0xb36535f1,0xb6aa31db,0x3b463bdd,0xaf0eb94d,0xbbf4b9fe,0xbbf8bae9,0xad7e3807,
0x394d3baf,0x39fe3475,0x38d82d7e,0xba5ebbf8,0xb64e3115,0x3b5a3be6,0x3bd43b80,0x32a1b593,0xbbffba99,0x28b63887,0x336539ba,0x3bc93996,0xb75ebae9,0xbb1ab807,0xba3fb534,0x39003b91,
0x39ba3bbc,0x39963414,0x31dbb534,0xbbddbb91,0xb3653475,0x3bc93baf,0x3b803927,0xb593ba1f,0xbba0b972,0x34d539dc,0x3a3f3be6,0x39003115,0xb9febbd4,0xb94db2a1,0xb04e35f1,0x3bed3b6e,
0x3a1f3bc9,0x39273365,0xb475b972,0xbbafb9dc,0xabd9364e,0x3bfc3b5a,0x38d831db,0xba5ebbdd,0xbab5b807,0x385d3ae9,0x3c003b30,0x2248b705,0xbb80bbf4,0xb5932f0e,0x38b03b1a,0x3a7c375e,
0x3a7c3bd4,0x38b032a1,0xb972bb5a,0xb9dcb64e,0x2f0e3807,0x3bf43ae9,0x2d7eb534,0xbbf8bb91,0xb94db4d5,0x39fe3ba0,0x3a5e37b7,0xb8d8bb02,0xbc00bb46,0x224836aa,0x3bdd3bc9,0x31dbb365,
0x3ad03bdd,0x383231db,0xbb80bc00,0xb5932248,0x347538d8,0x3baf3a5e,0xb75eb9fe,0xbb1ab94d,0xb705ad7e,0x3b303bf8,0x3414af0e,0xbbbcbbf4,0xbb6eb9dc,0x35f13972,0x3ab538b0,0xb85dba7c,
0x3b1a3be6,0x375e3115,0xbbf4bb46,0x2f0e36aa,0x37053996,0x3b3039ba,0xbae9bbd4,0xb807b2a1,0xb1db304e,0x3bdd3bed,0xb64eb94d,0xbb5ab9fe,0xb9dcb7b7,0x39723b02,0x3365ad7e,0xbbc9bbf8,
0x3b5a3bed,0x364e304e,0xbab5b94d,0x385d39fe,0x38b03a3f,0x3a7c3900,0xbbffbba0,0x28b634d5,0x2d7e3593,0x3bf83b80,0xbb02bbc9,0xb7b7b365,0xb705b1db,0x3b303bdd,0xb807b9ba,0xbae9b996,
0x3b913bf4,0x35342f0e,0xb807b4d5,0x3ae93ba0,0x39ba3ad0,0x39963832,0xba99b972,0x388739dc,0x3593385d,0x3b803ab5,0xbbe6bb6e,0x311535f1,0xad7e304e,0x3bf83bed,0xbbafbbfc,0xb475abd9,
0x3bbc3bf8,0x34142d7e,0xabd92f0e,0x3bfc3bf4,0x3a993b46,0x388736aa,0xb64eb365,0x3b5a3bc9,0x38b039ba,0x3a7c3996,0xb972b85d,0x39dc3ab5,0x34753705,0x3baf3b30,0xbb1aba5e,0x375e38d8,
0x3bdd3bfc,0x31db2bd9,0x364e3807,0x3b5a3ae9,0x3b463ba0,0x36aa34d5,0x31153475,0x3be63baf,0x3a3f3ad0,0x39003832,0xad7e28b6,0x3bf83bff,0x38d83996,0x3a5e39ba,0xb534b2a1,0x3b913bd4,
0x3bf43bff,0x2f0e28b6,0x3a1f3a7c,0x392738b0,0x3bbc3bdd,0x341431db,0x394d39ba,0x39fe3996,0x3b5a3b91,0x364e3534,0x385d38d8,0x3ab53a5e,0x3ad03b1a,0x3832375e,0x36aa37b7,0x3b463b02,
0x3bff3c00,0x28b62248,0x3bc93bd4,0x336532a1,0x3bf83bfc,0x2d7e2bd9,0x3baf3bbc,0x34753414,0x3bed3bf4,0x304e2f0e,0x3b913ba0,0x353434d5,0x3bdd3be6,0x31db3115,0x3b6e3b80,0x35f13593,
0xb5933b6e,0x3b8035f1,0xb1153bdd,0x3be631db,0x34d5bb91,0xbba0b534,0x2f0ebbed,0xbbf4b04e,0xb4143baf,0x3bbc3475,0xabd93bf8,0x3bfc2d7e,0x32a1bbc9,0xbbd4b365,0x2248bbff,0xbc00a8b6,
0x37b73b46,0x3b02b6aa,0x3b1a3832,0x375ebad0,0xb8d8bab5,0xba5e385d,0xbb91b64e,0xb5343b5a,0x39ba39fe,0x3996b94d,0x3bdd3414,0x31dbbbbc,0xba7cb927,0xb8b03a1f,0xbbffaf0e,0xa8b63bf4,
0x3bd43534,0x32a1bb91,0x39bab8d8,0xb996ba5e,0xbbffad7e,0x28b63bf8,0xb8323a3f,0x3ad03900,0x3bafb115,0xb475bbe6,0x34d5bb46,0xbba0b6aa,0xbae9364e,0x38073b5a,0xabd93bdd,0x3bfc31db,
0x3a5eb75e,0xb8d8bb1a,0xb705bbaf,0xbb303475,0xb85d39dc,0x3ab53972,0x39ba3a7c,0x3996b8b0,0x3365bb5a,0xbbc9b64e,0xbb46b887,0xb6aa3a99,0x2f0e3bfc,0x3bf42bd9,0x3bf83414,0x2d7ebbbc,
0x2bd9bbaf,0xbbfcb475,0xbbedad7e,0x304e3bf8,0x35f13be6,0x3b6eb115,0x3ab5b593,0xb85dbb80,0xb9dcba99,0xb9723887,0xb83239ba,0x3ad03996,0x3ba03807,0x34d5bae9,0x2f0ebb91,0xbbf4b534,
0xb9babae9,0xb9963807,0xb1db3b30,0x3bdd3705,0x3bc937b7,0x3365bb02,0xb593bbf8,0xbb802d7e,0xbba028b6,0x34d53bff,0x3a3f3a7c,0x3900b8b0,0x394db85d,0xb9febab5,0xbbedb64e,0xb04e3b5a,
0xbbf8b365,0x2d7e3bc9,0x3b0239dc,0x37b7b972,0x39feb64e,0xb94dbb5a,0xbbedb1db,0x304e3bdd,0xb2a13ae9,0x3bd43807,0x39bab705,0xb996bb30,0xb6aabbf4,0xbb462f0e,0xb1153b1a,0x3be6375e,
0xb8b0385d,0x3a7c3ab5,0x39dcb5f1,0xb972bb6e,0xaf0ebbbc,0xbbf4b414,0xad7e3b30,0x3bf83705,0x39fe3b1a,0x394db75e,0xb8d8bbaf,0xba5e3475,0xbc00b593,0x22483b80,0x3bdd3832,0x31dbbad0,
0x33653bdd,0x3bc931db,0xb6aabc00,0xbb462248,0xbb02ba5e,0xb7b738d8,0x3ba0394d,0x34d5b9fe,0x3b912d7e,0xb534bbf8,0xbae92f0e,0x38073bf4,0xb64e3972,0x3b5a39dc,0x32a1ba7c,0xbbd4b8b0,
0x3b1a3a7c,0x375eb8b0,0xbbf4b593,0x2f0e3b80,0xbb30a248,0x37053c00,0x3807b85d,0xbae9bab5,0x31dbba5e,0xbbddb8d8,0x364e3bfc,0x3b5a2bd9,0x39723baf,0x39dcb475,0xbbc9b927,0xb3653a1f,
0x3b6e304e,0xb5f1bbed,0xb2a139fe,0x3bd4394d,0xb1153a3f,0x3be63900,0xb9dcbba0,0xb97234d5,0xba1fbb80,0xb9273593,0x3baf3365,0xb475bbc9,0x3b9131db,0xb534bbdd,0xb41439ba,0x3bbc3996,
0x3534b900,0xbb91ba3f,0x3ae93b1a,0x3807b75e,0x39ba3bc9,0x3996b365,0xba9928b6,0x38873bff,0xbb80b2a1,0x35933bd4,0xb115bb5a,0xbbe6b64e,0x2d7eba5e,0xbbf8b8d8,0x3baf39fe,0x3475b94d,
0xb807bbf8,0xbae9ad7e,0x39feaf0e,0xb94dbbf4,0x3bdd36aa,0xb1dbbb46,0x35f13bc9,0x3b6e3365,0xb11539ba,0x3be63996,0xbbffb85d,0x28b63ab5,0xbb02bb30,0xb7b73705,0x34d5b8d8,0xbba0ba5e,
0xbbddb9fe,0xb1db394d,0xb64ebbbc,0xbb5ab414,0x36aab75e,0xbb46bb1a,0x3be637b7,0xb115bb02,0x3a3f3bc9,0x3900b365,0xad7e39dc,0x3bf83972,0xba5ea248,0x38d83c00,0xbb91bab5,0xb534385d,
0xba3fa8b6,0x39003bff,0xbbf8b8b0,0x2d7e3a7c,0xb807bbdd,0xbae9b1db,0x2bd9b9ba,0xbbfcb996,0x3b6e3534,0xb5f1bb91,0x3bd43a5e,0x32a1b8d8,0x33653b1a,0x3bc9375e,0xb59337b7,0x3b803b02,
0xa8b63996,0x3bff39ba,0xb365385d,0x3bc93ab5,0xbbf8b9fe,0xad7e394d,0xbbafbae9,0xb4753807,0x304eb900,0xbbedba3f,0x3534b75e,0xbb91bb1a,0x3bdd3a7c,0x31dbb8b0,0x3b6e3b46,0x35f1b6aa,
0x39dc3c00,0x3972a248,0x3ad03bd4,0x3832b2a1,0xb9272bd9,0x3a1f3bfc,0xb7b73414,0x3b023bbc,0xba5ebbf4,0xb8d82f0e,0xbb30bba0,0xb70534d5,0x3887b115,0xba99bbe6,0x364eb593,0xbb5abb80,
0x3bf43972,0xaf0eb9dc,0x3a1f3115,0xb927bbe6,0x34143a99,0x3bbc3887,0x39fe3c00,0x394d2248,0xbb5ab705,0x364e3b30,0xb85d304e,0x3ab53bed,0xb832bba0,0xbad0b4d5,0xbb46bbaf,0xb6aa3475,
0x3887abd9,0xba99bbfc,0xb5f1bae9,0xbb6eb807,0x3b803ba0,0x3593b4d5,0x3a7c3475,0xb8b0bbaf,0xaf0e3832,0x3bf43ad0,0x3a1f3bff,0x392728b6,0xbbedb996,0x304e39ba,0xb70532a1,0x3b303bd4,
0xb414ba1f,0xbbbcb927,0xbbfcba3f,0x2bd93900,0x3a993593,0xb887bb80,0xb64ebad0,0xbb5ab832,0x3a7c3c00,0x38b02248,0x39dc32a1,0xb972bbd4,0xb4753534,0x3baf3b91,0x3b1a3bed,0x375eb04e,
0xbb30bbf4,0xb7052f0e,0xb41434d5,0x3bbc3ba0,0x2248b832,0xbc00bad0,0xbbddb9dc,0x31db3972,0x3b46385d,0xb6aabab5,0xb8b0bb6e,0xba7cb5f1,0x3a1f3bed,0x3927304e,0x37b7abd9,0xbb02bbfc,
0xbb5ab8d8,0x364e3a5e,0x3ab53bfc,0x385d2bd9,0xba7cbbf4,0xb8b0af0e,0xa8b6375e,0x3bff3b1a,0x2d7eb6aa,0xbbf8bb46,0xbb02b832,0x37b73ad0,0x3b303887,0xb705ba99,0xbae9bc00,0xb807a248,
0xb4d53115,0x3ba03be6,0x3a3f36aa,0xb900bb46,0xbb91b996,0x353439ba,0x3bbc3bd4,0x3414b2a1,0xba99bbed,0xb887b04e,0x35f139fe,0x3b6e394d,0xa8b6b7b7,0xbbffbb02,0xb832ad7e,0x3ad03bf8,
0x38323a99,0x3ad03887,0xb593b996,0xbb80b9ba,0xb475304e,0x3baf3bed,0x375e2bd9,0xbb1abbfc,0xbb30b927,0x37053a1f,0x3bbc3a3f,0xb414b900,0xbb6ebbff,0xb5f128b6,0x3ab53be6,0x385d3115,
0x3be63bd4,0x3115b2a1,0xbbffbb5a,0x28b6364e,0x39003ae9,0x3a3f3807,0xba1fbb91,0xb927b534,0xabd934d5,0x3bfc3ba0,0xb04eb7b7,0xbbedbb02,0xb9bab6aa,0x39963b46,0x38873365,0xba99bbc9,
0x3a1f3832,0xb927bad0,0xb47528b6,0x3baf3bff,0x3bfc3b6e,0xabd9b5f1,0xba5eb887,0x38d83a99,0x3ab53bbc,0x385d3414,0xbc00bb91,0x22483534,0x35933900,0x3b803a3f,0xba7cbba0,0xb8b0b4d5,
0x2248b414,0xbc00bbbc,0x3a993b91,0x38873534,0x38323475,0xbad0bbaf,0x36aa3927,0x3b463a1f,0x3b1a39dc,0xb75eb972,0xaf0e3115,0x3bf43be6,0x3bfc3bd4,0x2bd9b2a1,0xb8d8b5f1,0x3a5e3b6e,
0xb9febb02,0xb94db7b7,0x3a5e3927,0xb8d8ba1f,0xb64eb8b0,0xbb5aba7c,0x3bd43b46,0xb2a1b6aa,0x28b6b1db,0xbbffbbdd,0x3bc93c00,0x33652248,0x375e3414,0xbb1abbbc,0x3a3f3b30,0x39003705,
0xbbedbba0,0x304e34d5,0xb534b7b7,0xbb91bb02,0xbbd4bbff,0xb2a1a8b6,0x2248b115,0xbc00bbe6,0xbad0bb6e,0xb832b5f1,0x359331db,0xbb80bbdd,0xb900b9fe,0xba3fb94d,0x39273807,0xba1fbae9,
0xb85db705,0x3ab53b30,0xbc00bbed,0x2248304e,0xb9dcb927,0x39723a1f,0xbbc9bbf4,0xb365af0e,0xbb02ba7c,0x37b738b0,0xbb1abb80,0xb75eb593,0xbbbcbb6e,0x341435f1,0xb9feba99,0xb94db887,
0x34753593,0x3baf3b80,0xb4d5b365,0x3ba03bc9,0x304e32a1,0x3bed3bd4,0xb705b5f1,0x3b303b6e,0xa2482bd9,0x3c003bfc,0xb887b807,0x3a993ae9,0xb115ad7e,0x3be63bf8,0xb972b900,0x39dc3a3f,
0x3b463b5a,0x36aa364e,0x3a7c3a99,0x38b03887,0x3b1a3b30,0x375e3705,0x3a3f3a5e,0x390038d8,0x3ae93b02,0x380737b7,0x39fe3a1f,0x394d3927,0x3ab53ad0,0x385d3832,0x39ba39dc,0x39963972,
0x28b63c00,0x3bffa248,0x33653bd4,0x3bc9b2a1,0xad7ebbfc,0xbbf82bd9,0xb475bbbc,0xbbaf3414,0x304e3bf4,0x3bedaf0e,0x35343ba0,0x3b91b4d5,0xb1dbbbe6,0xbbdd3115,0xb5f1bb80,0xbb6e3593,
0x3bf4a8b6,0xaf0ebbff,0x3a1fb8b0,0xb927ba7c,0xbbbc31db,0x34143bdd,0xb94d3996,0x39fe39ba,0x3b5ab534,0xb64ebb91,0x385dba5e,0xbab5b8d8,0xbad0375e,0x38323b1a,0xb6aa3b02,0x3b4637b7,
0xb1dbbbfc,0xbbdd2bd9,0xbb5ab807,0xb64e3ae9,0x36aa3ba0,0x3b46b4d5,0x3be63475,0x3115bbaf,0xb900bad0,0xba3f3832,0xbbf8a8b6,0x2d7e3bff,0x3a5e3996,0x38d8b9ba,0x3b91b2a1,0xb534bbd4,
0xbbbc2d7e,0x34143bf8,0x2bd93bf4,0x3bfc2f0e,0x3a99b6aa,0xb887bb46,0xb64ebbc9,0xbb5a3365,0xb8b03996,0x3a7c39ba,0x39723ab5,0x39dcb85d,0x3475bb30,0xbbafb705,0xbb1ab8d8,0xb75e3a5e,
0x35343bf4,0x3b91af0e,0x3ae9b4d5,0xb807bba0,0xb996bad0,0xb9ba3832,0xb8873972,0x3a9939dc,0x3b80385d,0x3593bab5,0x3115bb6e,0xbbe6b5f1,0xbbf8b04e,0x2d7e3bed,0x34753bfc,0x3bafabd9,
0x3b5ab04e,0xb64ebbed,0xbab5b9fe,0xb85d394d,0xb8b03900,0x3a7c3a3f,0x3bff34d5,0x28b6bba0,0x2d7ebb80,0xbbf8b593,0xbb023365,0x37b73bc9,0x37053bdd,0x3b30b1db,0x3807b996,0xbae9b9ba,
0xb75ebbe6,0xbb1a3115,0xaf0e3b46,0x3bf436aa,0x3b303996,0x3705b9ba,0xb807bbd4,0xbae932a1,0xbbddb04e,0x31db3bed,0x3b5a394d,0x364eb9fe,0x3972b7b7,0xb9dcbb02,0xbbc9ad7e,0x33653bf8,
0xbad031db,0x38323bdd,0x3b802248,0xb593bc00,0x3475ba5e,0xbbafb8d8,0xb75e394d,0x3b1a39fe,0x37053bf8,0x3b30ad7e,0xb414bbf4,0xbbbcaf0e,0xbb6eb972,0xb5f139dc,0x3ab53a7c,0x385db8b0,
0x38b03bd4,0x3a7cb2a1,0xb9dcbb5a,0xb972364e,0xbbf4b807,0xaf0e3ae9,0x3bf83534,0xad7ebb91,0x39feb4d5,0xb94dbba0,0xb8d837b7,0x3a5e3b02,0xa2483b46,0x3c0036aa,0xb1dbbbc9,0xbbddb365,
0x3a1fb365,0xb927bbc9,0xb47539dc,0x3baf3972,0x2bd93b5a,0x3bfc364e,0xb8d8bbdd,0xba5e31db,0xbab5bae9,0xb85d3807,0x3c003705,0xa248bb30,0x3b802f0e,0xb593bbf4,0xb8b0375e,0x3a7c3b1a,
0xb996bbbc,0xb9ba3414,0x3bdd3534,0xb1dbbb91,0x3bc93475,0xb365bbaf,0xb5933927,0x3b803a1f,0xb4d53972,0x3ba039dc,0xb900bbe6,0xba3f3115,0xb94dbbd4,0xb9fe32a1,0x3bed35f1,0xb04ebb6e,
0xb94d3475,0x39fe3baf,0xb8d8bbf8,0xba5e2d7e,0xb64ebbe6,0xbb5ab115,0x3bd43593,0xb2a1bb80,0x3bff3887,0x28b6ba99,0xb3653996,0x3bc939ba,0xb75e3807,0x3b1a3ae9,0xba3fbb91,0xb9003534,
0x3a5e3ba0,0x38d8b4d5,0xb70537b7,0x3b303b02,0xbab5a8b6,0x385d3bff,0xb996bbe6,0xb9ba3115,0xb365bb6e,0xbbc9b5f1,0x3b4631db,0xb6aabbdd,0x3bf4394d,0x2f0eb9fe,0x2d7e3ae9,0x3bf83807,
0x385db534,0xbab5bb91,0x3c0038d8,0xa248ba5e,0x39723bf8,0x39dcad7e,0xb3653900,0x3bc93a3f,0xbb02b115,0x37b73be6,0xbb1abb46,0xb75e36aa,0xb414bb5a,0xbbbcb64e,0x394db1db,0xb9febbdd,
0xbb02bb80,0xb7b73593,0xb75ebbc9,0xbb1ab365,0x38d8b2a1,0xba5ebbd4,0x3b9135f1,0xb534bb6e,0x39963bfc,0x39baabd9,0x31db3ae9,0x3bdd3807,0xba7cad7e,0x38b03bf8,0xbbffb900,0x28b63a3f,
0xb6aa35f1,0x3b463b6e,0xb8b031db,0x3a7c3bdd,0xbb1abb91,0xb75e3534,0xba3fbbed,0xb900304e,0x3807b475,0xbae9bbaf,0x394dad7e,0xb9febbf8,0x3ab53bc9,0x385db365,0x39ba3bff,0x3996a8b6,
0x3b803b5a,0x3593b64e,0x3be63a99,0x3115b887,0xb4d53705,0x3ba03b30,0xaf0e38d8,0x3bf43a5e,0xbbbcbb02,0xb41437b7,0xbbfcba1f,0xabd93927,0x32a1b832,0xbbd4bad0,0x2248b972,0xbc00b9dc,
0x3475b6aa,0xbbafbb46,0xb4d5bad0,0xbba0b832,0x3bed3ab5,0x304eb85d,0x3b30364e,0xb705bb5a,0x2248394d,0x3c0039fe,0x38873bbc,0x3a993414,0xbbe6b927,0x31153a1f,0xb9dcaf0e,0x39723bf4,
0xbbd4bb30,0xb2a13705,0xb9bab04e,0x39963bed,0xa8b6b927,0xbbffba1f,0xbad0bbf4,0xb8322f0e,0x3baf38b0,0xb475ba7c,0x34d5b593,0xbba0bb80,0x38073b6e,0x3ae935f1,0x3bfc3a99,0x2bd9b887,
0xb04e375e,0x3bed3b1a,0x3b913baf,0x3534b475,0xbbd4b972,0x32a139dc,0x224838b0,0x3c003a7c,0xb832bb5a,0xbad0b64e,0xbb80b887,0x35933a99,0x39002bd9,0xba3fbbfc,0xb927bbbc,0xba1fb414,
0x3bfc3b02,0x2bd9b7b7,0xb04eb927,0xbbedba1f,0x35f13a7c,0x3b6e38b0,0x3ab536aa,0xb85dbb46,0xb972b1db,0x39dc3bdd,0x3ad03c00,0x3832a248,0xbba0bbbc,0xb4d53414,0xaf0e3705,0x3bf43b30,
0xa248b807,0xbc00bae9,0xba99b705,0x38873b30,0x3ad037b7,0xb832bb02,0xbb46bbf8,0xb6aa2d7e,0x3b1a3bff,0x375ea8b6,0xaf0eb8b0,0xbbf4ba7c,0x2bd9385d,0x3bfc3ab5,0x3a5e364e,0xb8d8bb5a,
0xbbf8bad0,0x2d7e3832,0x3b023bff,0x37b728b6,0xb94dbb6e,0xb9feb5f1,0x304e3887,0x3bed3a99,0x32a1b414,0xbbd4bbbc,0xb9bab534,0x39963b91,0x3b463900,0xb6aaba3f,0xbbe6bba0,0xb11534d5,
0x3115385d,0x3be63ab5,0x28b6b5f1,0xbbffbb6e,0xb900b414,0x3a3f3bbc,0x3a1f3705,0xb927bb30,0xbbfcbb1a,0x2bd9375e,0x3bed3baf,0x304eb475,0xb9babb80,0xb996b593,0x38873ad0,0x3a993832,
0x3bc93a99,0xb365b887,0xbb46b996,0x36aa39ba,0x3b023bed,0x37b7304e,0xbba0bbfc,0xb4d52bd9,0x35343927,0x3b913a1f,0xb807ba3f,0xbae9b900,0xb64ea8b6,0x3b5a3bff,0x32a1b115,0xbbd4bbe6,
0xb4d5b8b0,0xbba0ba7c,0x3a3f3b80,0x39003593,0x35342248,0xbb91bc00,0x3414385d,0x3bbc3ab5,0x3a9938d8,0xb887ba5e,0xb5f1abd9,0x3b6e3bfc,0x3bff3baf,0x28b6b475,0xbad0b927,0x38323a1f,
0xbb6eba5e,0x35f138d8,0x32a1abd9,0xbbd4bbfc,0xbbe6bbf4,0xb1152f0e,0x3972375e,0xb9dcbb1a,0xba1fbb46,0xb927b6aa,0x3baf3ad0,0xb475b832,0xb534b887,0xbb91ba99,0x3bbc3c00,0x3414a248,
0x37053900,0x3b303a3f,0xbbbcbb1a,0x3414375e,0x22483365,0x3c003bc9,0xbbddbbff,0xb1db28b6,0xb6aab2a1,0x3b463bd4,0xba7cbb5a,0xb8b0b64e,0xba1fb8d8,0x39273a5e,0xb7b7b94d,0xbb02b9fe,
0x3ae93a1f,0xb807b927,0x394d3a3f,0x39fe3900,0x3bdd3b80,0xb1dbb593,0x35f13832,0x3b6e3ad0,0x3be63c00,0x3115a248,0x28b632a1,0x3bff3bd4,0x3b023b91,0x37b73534,0xb4d5b04e,0x3ba03bed,
0xb887b94d,0xba99b9fe,0x35f13414,0xbb6ebbbc,0xb593b75e,0xbb80bb1a,0x38b037b7,0xba7cbb02,0xaf0eb365,0xbbf4bbc9,0x3a1f3972,0xb927b9dc,0x304e2248,0xbbedbc00,0x3b303ab5,0xb705b85d,
0xba3fb9dc,0x39003972,0xbbf8bbe6,0x2d7e3115,0xbae9ba99,0x38073887,0xbbfcbc00,0xabd92248,0xbb6ebb30,0x35f13705,0xbbd4bbed,0xb2a1b04e,0xbbc9bba0,0x336534d5,0xbb80bbaf,0xb593b475,
0x39723996,0x39dc39ba,0x3832385d,0x3ad03ab5,0x3927394d,0x3a1f39fe,0x37b73807,0x3b023ae9,0x38d83900,0x3a5e3a3f,0x3705375e,0x3b303b1a,0x388738b0,0x3a993a7c,0x364e36aa,0x3b5a3b46,
0x36aa3b5a,0x3b46b64e,0x38b03a99,0x3a7cb887,0xb75ebb30,0xbb1a3705,0xb900ba5e,0xba3f38d8,0x38073b02,0x3ae9b7b7,0x394d3a1f,0x39feb927,0xb85dbad0,0xbab53832,0xb996b9dc,0xb9ba3972,
0x3475bb80,0xbbafb593,0xb4d5bbc9,0xbba03365,0xb04e3bd4,0x3bed32a1,0x37053b6e,0x3b30b5f1,0xa248bbfc,0xbc00abd9,0xb887bae9,0xba993807,0x31153bf8,0x3be6ad7e,0x39723a3f,0x39dcb900,
0xbab53705,0x385d3b30,0xa2483bed,0x3c00304e,0x3972b927,0xb9dcba1f,0xb365bbf4,0xbbc92f0e,0xb7b73a7c,0x3b0238b0,0x375e3b80,0x3b1ab593,0x3414bb6e,0xbbbcb5f1,0xb94dba99,0xb9fe3887,
0x3bed34d5,0x304ebba0,0x3534bb02,0xbb91b7b7,0xbbd428b6,0x32a13bff,0x22483be6,0x3c003115,0x3ad0b5f1,0xb832bb6e,0xb593bbdd,0xbb8031db,0xb900394d,0x3a3f39fe,0x39273ae9,0x3a1fb807,
0xb94dbb02,0xb9fe37b7,0xb8d83927,0x3a5e3a1f,0x3b5a38b0,0x364eba7c,0x32a1bb46,0xbbd4b6aa,0xbbffb1db,0x28b63bdd,0x33653c00,0x3bc9a248,0x3b1ab414,0xb75ebbbc,0xb900bb30,0xba3f3705,
0x22483bbc,0x3c003414,0x3a99b534,0xb887bb91,0xb832bbaf,0xbad03475,0xb6aa3a1f,0x3b463927,0x3b1a3972,0x375eb9dc,0xaf0ebbe6,0xbbf4b115,0xbbfcb2a1,0x2bd93bd4,0x38d83b6e,0x3a5eb5f1,
0x3927b832,0xba1fbad0,0xbbafa8b6,0x34753bff,0xabd93b6e,0x3bfc35f1,0x38d8b887,0xba5eba99,0xb85dbbbc,0xbab53414,0xa2483b91,0x3c003534,0x3b803900,0x3593ba3f,0xb8b0bba0,0xba7c34d5,
0xbbe6b2a1,0x31153bd4,0x3bff364e,0x28b6bb5a,0x3900b807,0xba3fbae9,0xba1f3534,0x39273b91,0x2bd93ba0,0x3bfc34d5,0x304ebb02,0xbbedb7b7,0xb9babb46,0xb99636aa,0x38873bc9,0x3a99b365,
0x3ad03a99,0x3832b887,0xbb80b996,0xb59339ba,0xbbafb04e,0x34753bed,0x3b1aabd9,0xb75ebbfc,0x3705b927,0xbb30ba1f,0xb4143a3f,0x3bbc3900,0x35f13bff,0x3b6e28b6,0xb85dbbe6,0xbab53115,
0xb4d5bbe6,0xbba0b115,0x3a3f3b46,0x3900b6aa,0x3b9139ba,0x3534b996,0xbbbcb2a1,0x34143bd4,0xba99304e,0x38873bed,0x35f1b94d,0xbb6eb9fe,0x28b6bb02,0xbbffb7b7,0x38323bf8,0x3ad0ad7e,
0xb64e38d8,0x3b5a3a5e,0xb85dbbfc,0xbab52bd9,0xb8b0bbf4,0xba7c2f0e,0x3bff375e,0xa8b6bb1a,0x3bf836aa,0xad7ebb46,0xb7b73832,0x3b023ad0,0xb7053887,0x3b303a99,0xb807bc00,0xbae92248,
0x3b302f0e,0xb705bbf4,0x34143ba0,0x3bbc34d5,0x22483ad0,0x3c003832,0xbbddb972,0xb1db39dc,0xbb46bab5,0xb6aa385d,0x38b0b5f1,0xba7cbb6e,0x3a1fb04e,0xb927bbed,0x37b73bfc,0x3b022bd9,
0xbbbcba1f,0xb4143927,0x2bd9ba3f,0xbbfcb900,0x3887b593,0xba99bb80,0x3b5a3ad0,0x364eb832,0x38b03c00,0x3a7ca248,0xb97232a1,0x39dc3bd4,0xbbafb534,0x34753b91,0xb75ebbed,0xbb1ab04e,
0x38873bfc,0x3a992bd9,0xb5f13807,0x3b6e3ae9,0xbb80b4d5,0x35933ba0,0xba7cbbaf,0xb8b03475,0xaf0ebad0,0xbbf4b832,0x3a1fa8b6,0xb927bbff,0x3bed39ba,0x304eb996,0x37053bd4,0x3b3032a1,
0x2f0eb972,0xbbf4b9dc,0x3927b115,0xba1fbbe6,0x3bbc3a99,0x3414b887,0x394d3c00,0x39fea248,0xb64e3705,0x3b5a3b30,0xbab5b04e,0x385d3bed,0xbad0bba0,0xb83234d5,0xb6aabbaf,0xbb46b475,
0xb9dca248,0x39723c00,0xbad0b2a1,0x38323bd4,0xb927bbfc,0xba1fabd9,0xb7b7bbbc,0xbb02b414,0x3a5e2f0e,0xb8d8bbf4,0x3b3034d5,0xb705bba0,0x38873be6,0x3a993115,0x364e3b80,0x3b5a3593,
0x3bff3996,0xa8b6b9ba,0x3bc9385d,0xb365bab5,0x2d7e39fe,0x3bf8394d,0x34753ae9,0x3baf3807,0xbbedb900,0x304e3a3f,0xbb91b75e,0x35343b1a,0xb1dbba7c,0xbbddb8b0,0xb5f1bb46,0xbb6eb6aa,
0xba3fbbff,0xb90028b6,0xbbf8ba7c,0xad7e38b0,0x3807b1db,0xbae9bbdd,0xabd9b996,0xbbfcb9ba,0x3b6e3b91,0x35f1b534,0x3bd438d8,0xb2a1ba5e,0xb365375e,0x3bc93b1a,0x35933b02,0x3b8037b7,
0x31db39fe,0x3bdd394d,0x3b5a3bbc,0x364eb414,0xbb46b75e,0x36aa3b1a,0xb11537b7,0x3be63b02,0xb900bbc9,0xba3fb365,0xbbf8b9dc,0x2d7e3972,0x38d8a248,0xba5ebc00,0xb534bab5,0xbb91b85d,
0x3807ad7e,0xbae9bbf8,0xb9febbf4,0xb94daf0e,0x3bdd3b46,0x31dbb6aa,0x35f1b365,0xbb6ebbc9,0x31153996,0x3be639ba,0x3bff3ab5,0x28b6b85d,0xbb02b705,0x37b73b30,0x34d53a5e,0x3ba038d8,
0xbb91b900,0x35343a3f,0x38073b1a,0x3ae9375e,0xb996bbc9,0xb9bab365,0xb887a8b6,0x3a993bff,0x3593b2a1,0xbb80bbd4,0xbbe6bb5a,0xb115364e,0x3bf83a5e,0xad7eb8d8,0xb475b9fe,0xbbafb94d,
0x3b6e3bed,0x35f1b04e,0xb2a1b94d,0xbbd4b9fe,0x31153900,0x3be63a3f,0x39dc34d5,0xb972bba0,0xba1fb593,0x39273b80,0x3baf3bc9,0x3475b365,0xbb91bbdd,0xb53431db,0x34143996,0x3bbc39ba,
0xb75eba7c,0xbb1ab8b0,0xaf0e3593,0x3bf43b80,0x3705a248,0xbb30bc00,0xbae9b85d,0x38073ab5,0x3bdd3a5e,0xb1dbb8d8,0xbb5abbfc,0xb64e2bd9,0x39dc3baf,0x39723475,0xb365b927,0xbbc9ba1f,
0xb36531db,0x3bc93bdd,0x36aa2248,0xbb46bc00,0xbb02b8d8,0x37b73a5e,0x3ba039fe,0xb4d5b94d,0xbb91bbf8,0xb5342d7e,0x3ae93bf4,0x38072f0e,0xb64eb9dc,0xbb5ab972,0x32a138b0,0x3bd43a7c,
0x3a7c385d,0xb8b0bab5,0xb972b5f1,0x39dc3b6e,0x3bf43bbc,0x2f0eb414,0xbbf8bb30,0x2d7e3705,0x394d3b1a,0x39fe375e,0xba5ebbaf,0xb8d8b475,0xa2483593,0x3c003b80,0xb1dbb832,0xbbddbad0,
0xbbf8bbc9,0xad7e3365,0x3b023972,0xb7b7b9dc,0xb9febb5a,0xb94db64e,0x3bed3bdd,0x304eb1db,0xb2a1b807,0xbbd4bae9,0x39ba3b30,0x39963705,0x36aa2f0e,0xbb46bbf4,0x3115375e,0x3be63b1a,
0x39963ae9,0x39ba3807,0xbbddbb30,0x31db3705,0x336537b7,0x3bc93b02,0xbb80bbf8,0xb593ad7e,0xb4d5a8b6,0x3ba03bff,0xb900ba7c,0xba3fb8b0,0xb9feb85d,0x394d3ab5,0xb04eb64e,0xbbedbb5a,
0xabd9b475,0xbbfcbbaf,0x3bed3bf8,0x304ead7e,0x35f13115,0xbb6ebbe6,0x3ab53b80,0x385d3593,0x39dc3887,0xb972ba99,0x38323996,0x3ad039ba,0x3ba03ae9,0xb4d5b807,0x2f0e3534,0x3bf43b91,
0xb8d8b75e,0x3a5e3b1a,0xbb30bbaf,0xb705b475,0xbab5b9dc,0x385d3972,0xb996ba7c,0xb9bab8b0,0xbbc9bb5a,0x3365364e,0xb6aab887,0xbb46ba99,0xbbf4bbfc,0xaf0e2bd9,0xad7eb414,0xbbf8bbbc,
0x3bd43b91,0xb2a1b534,0x39ba3a5e,0x399638d8,0x3bff3bf8,0x28b6ad7e,0x38323900,0x3ad03a3f,0x3baf3be6,0x34753115,0x34d536aa,0x3ba03b46,0x3ae93b5a,0x3807364e,0x2bd931db,0x3bfc3bdd,
0xbb02bb46,0xb7b7b6aa,0xb75eb832,0xbb1abad0,0xba5ebab5,0xb8d8b85d,0xb534b64e,0xbb91bb5a,0xb996b9fe,0xb9bab94d,0xb1dbb414,0xbbddbbbc,0xb8b0b927,0xba7cba1f,0xa8b6af0e,0xbbffbbf4,
0x359335f1,0x3b803b6e,0x311531db,0x3be63bdd,0x34d53534,0x3ba03b91,0x2f0e304e,0x3bf43bed,0x34143475,0x3bbc3baf,0x2bd92d7e,0x3bfc3bf8,0x32a13365,0x3bd43bc9,0x224828b6,0x3c003bff,
0x80000,0x680060,0xc800c0,0x1280120,0xc0004,0x6c0064,0xcc00c4,0x12c0124,0x180010,0x780070,0xd800d0,0x1380130,0x1c0014,0x7c0074,0xdc00d4,0x13c0134,
0x1880180,0x1e801e0,0x2480240,0x2a802a0,0x18c0184,0x1ec01e4,0x24c0244,0x2ac02a4,0x1980190,0x1f801f0,0x2580250,0x2b802b0,0x19c0194,0x1fc01f4,0x25c0254,0x2bc02b4,
0x3080300,0x3680360,0x3c803c0,0x4280420,0x30c0304,0x36c0364,0x3cc03c4,0x42c0424,0x3180310,0x3780370,0x3d803d0,0x4380430,0x31c0314,0x37c0374,0x3dc03d4,0x43c0434,
0x4880480,0x4e804e0,0x5480540,0x5a805a0,0x48c0484,0x4ec04e4,0x54c0544,0x5ac05a4,0x4980490,0x4f804f0,0x5580550,0x5b805b0,0x49c0494,0x4fc04f4,0x55c0554,0x5bc05b4,
0x6080600,0x6680660,0x6c806c0,0x7280720,0x60c0604,0x66c0664,0x6cc06c4,0x72c0724,0x6180610,0x6780670,0x6d806d0,0x7380730,0x61c0614,0x67c0674,0x6dc06d4,0x73c0734,
0x7880780,0x7e807e0,0x8480840,0x8a808a0,0x78c0784,0x7ec07e4,0x84c0844,0x8ac08a4,0x7980790,0x7f807f0,0x8580850,0x8b808b0,0x79c0794,0x7fc07f4,0x85c0854,0x8bc08b4,
0x9080900,0x9680960,0x9c809c0,0xa280a20,0x90c0904,0x96c0964,0x9cc09c4,0xa2c0a24,0x9180910,0x9780970,0x9d809d0,0xa380a30,0x91c0914,0x97c0974,0x9dc09d4,0xa3c0a34,
0xa880a80,0xae80ae0,0xb480b40,0xba80ba0,0xa8c0a84,0xaec0ae4,0xb4c0b44,0xbac0ba4,0xa980a90,0xaf80af0,0xb580b50,0xbb80bb0,0xa9c0a94,0xafc0af4,0xb5c0b54,0xbbc0bb4,
0x280020,0x880080,0xe800e0,0x1480140,0x2c0024,0x8c0084,0xec00e4,0x14c0144,0x240020,0x840080,0xe400e0,0x1440140,0x800024,0xe00084,0x14000e4,0x1a00144,
0x1a801a0,0x2080200,0x2680260,0x2c802c0,0x1ac01a4,0x20c0204,0x26c0264,0x2cc02c4,0x1a401a0,0x2040200,0x2640260,0x2c402c0,0x20001a4,0x2600204,0x2c00264,0x32002c4,
0x3280320,0x3880380,0x3e803e0,0x4480440,0x32c0324,0x38c0384,0x3ec03e4,0x44c0444,0x3240320,0x3840380,0x3e403e0,0x4440440,0x3800324,0x3e00384,0x44003e4,0x4a00444,
0x4a804a0,0x5080500,0x5680560,0x5c805c0,0x4ac04a4,0x50c0504,0x56c0564,0x5cc05c4,0x4a404a0,0x5040500,0x5640560,0x5c405c0,0x50004a4,0x5600504,0x5c00564,0x62005c4,
0x6280620,0x6880680,0x6e806e0,0x7480740,0x62c0624,0x68c0684,0x6ec06e4,0x74c0744,0x6240620,0x6840680,0x6e406e0,0x7440740,0x6800624,0x6e00684,0x74006e4,0x7a00744,
0x7a807a0,0x8080800,0x8680860,0x8c808c0,0x7ac07a4,0x80c0804,0x86c0864,0x8cc08c4,0x7a407a0,0x8040800,0x8640860,0x8c408c0,0x80007a4,0x8600804,0x8c00864,0x92008c4,
0x9280920,0x9880980,0x9e809e0,0xa480a40,0x92c0924,0x98c0984,0x9ec09e4,0xa4c0a44,0x9240920,0x9840980,0x9e409e0,0xa440a40,0x9800924,0x9e00984,0xa4009e4,0xaa00a44,
0xaa80aa0,0xb080b00,0xb680b60,0xbc80bc0,0xaac0aa4,0xb0c0b04,0xb6c0b64,0xbcc0bc4,0xaa40aa0,0xb040b00,0xb640b60,0xbc40bc0,0xb000aa4,0xb600b04,0xbc00b64,0x300bc4,
0x300030,0x900090,0xf000f0,0x1500150,0x900034,0xf00094,0x15000f4,0x1b00154,0x340030,0x940090,0xf400f0,0x1540150,0x900034,0xf00094,0x15000f4,0x1b00154,
0x1b001b0,0x2100210,0x2700270,0x2d002d0,0x21001b4,0x2700214,0x2d00274,0x33002d4,0x1b401b0,0x2140210,0x2740270,0x2d402d0,0x21001b4,0x2700214,0x2d00274,0x33002d4,
0x3300330,0x3900390,0x3f003f0,0x4500450,0x3900334,0x3f00394,0x45003f4,0x4b00454,0x3340330,0x3940390,0x3f403f0,0x4540450,0x3900334,0x3f00394,0x45003f4,0x4b00454,
0x4b004b0,0x5100510,0x5700570,0x5d005d0,0x51004b4,0x5700514,0x5d00574,0x63005d4,0x4b404b0,0x5140510,0x5740570,0x5d405d0,0x51004b4,0x5700514,0x5d00574,0x63005d4,
0x6300630,0x6900690,0x6f006f0,0x7500750,0x6900634,0x6f00694,0x75006f4,0x7b00754,0x6340630,0x6940690,0x6f406f0,0x7540750,0x6900634,0x6f00694,0x75006f4,0x7b00754,
0x7b007b0,0x8100810,0x8700870,0x8d008d0,0x81007b4,0x8700814,0x8d00874,0x93008d4,0x7b407b0,0x8140810,0x8740870,0x8d408d0,0x81007b4,0x8700814,0x8d00874,0x93008d4,
0x9300930,0x9900990,0x9f009f0,0xa500a50,0x9900934,0x9f00994,0xa5009f4,0xab00a54,0x9340930,0x9940990,0x9f409f0,0xa540a50,0x9900934,0x9f00994,0xa5009f4,0xab00a54,
0xab00ab0,0xb100b10,0xb700b70,0xbd00bd0,0xb100ab4,0xb700b14,0xbd00b74,0x380bd4,0xab40ab0,0xb140b10,0xb740b70,0xbd40bd0,0xb100ab4,0xb700b14,0xbd00b74,0x380bd4,
0x380038,0x980098,0xf800f8,0x1580158,0x98003c,0xf8009c,0x15800fc,0x1b8015c,0x3c0038,0x9c0098,0xfc00f8,0x15c0158,0x98003c,0xf8009c,0x15800fc,0x1b8015c,
0x1b801b8,0x2180218,0x2780278,0x2d802d8,0x21801bc,0x278021c,0x2d8027c,0x33802dc,0x1bc01b8,0x21c0218,0x27c0278,0x2dc02d8,0x21801bc,0x278021c,0x2d8027c,0x33802dc,
0x3380338,0x3980398,0x3f803f8,0x4580458,0x398033c,0x3f8039c,0x45803fc,0x4b8045c,0x33c0338,0x39c0398,0x3fc03f8,0x45c0458,0x398033c,0x3f8039c,0x45803fc,0x4b8045c,
0x4b804b8,0x5180518,0x5780578,0x5d805d8,0x51804bc,0x578051c,0x5d8057c,0x63805dc,0x4bc04b8,0x51c0518,0x57c0578,0x5dc05d8,0x51804bc,0x578051c,0x5d8057c,0x63805dc,
0x6380638,0x6980698,0x6f806f8,0x7580758,0x698063c,0x6f8069c,0x75806fc,0x7b8075c,0x63c0638,0x69c0698,0x6fc06f8,0x75c0758,0x698063c,0x6f8069c,0x75806fc,0x7b8075c,
0x7b807b8,0x8180818,0x8780878,0x8d808d8,0x81807bc,0x878081c,0x8d8087c,0x93808dc,0x7bc07b8,0x81c0818,0x87c0878,0x8dc08d8,0x81807bc,0x878081c,0x8d8087c,0x93808dc,
0x9380938,0x9980998,0x9f809f8,0xa580a58,0x998093c,0x9f8099c,0xa5809fc,0xab80a5c,0x93c0938,0x99c0998,0x9fc09f8,0xa5c0a58,0x998093c,0x9f8099c,0xa5809fc,0xab80a5c,
0xab80ab8,0xb180b18,0xb780b78,0xbd80bd8,0xb180abc,0xb780b1c,0xbd80b7c,0x400bdc,0xabc0ab8,0xb1c0b18,0xb7c0b78,0xbdc0bd8,0xb180abc,0xb780b1c,0xbd80b7c,0x400bdc,
0xacc0acc,0xb2c0b2c,0xb8c0b8c,0xbec0bec,0xb2c0acc,0xb8c0b8c,0xbec0b8c,0x500050,0xacc0acc,0xb2c0b2c,0xb8c0b8c,0xbec0bec,0xb2c0b2c,0xb8c0b8c,0xbec0bec,0x500050,
0x94c094c,0x9ac09ac,0xa0c0a0c,0xa6c0a6c,0x9ac094c,0xa0c0a0c,0xa6c0a0c,0xacc0acc,0x94c094c,0x9ac09ac,0xa0c0a0c,0xa6c0a6c,0x9ac09ac,0xa0c0a0c,0xa6c0a6c,0xacc0acc,
0x7cc07cc,0x82c082c,0x88c088c,0x8ec08ec,0x82c07cc,0x88c088c,0x8ec088c,0x94c094c,0x7cc07cc,0x82c082c,0x88c088c,0x8ec08ec,0x82c082c,0x88c088c,0x8ec08ec,0x94c094c,
0x64c064c,0x6ac06ac,0x70c070c,0x76c076c,0x6ac064c,0x70c070c,0x76c070c,0x7cc07cc,0x64c064c,0x6ac06ac,0x70c070c,0x76c076c,0x6ac06ac,0x70c070c,0x76c076c,0x7cc07cc,
0x4cc04cc,0x52c052c,0x58c058c,0x5ec05ec,0x52c04cc,0x58c058c,0x5ec058c,0x64c064c,0x4cc04cc,0x52c052c,0x58c058c,0x5ec05ec,0x52c052c,0x58c058c,0x5ec05ec,0x64c064c,
0x34c034c,0x3ac03ac,0x40c040c,0x46c046c,0x3ac034c,0x40c040c,0x46c040c,0x4cc04cc,0x34c034c,0x3ac03ac,0x40c040c,0x46c046c,0x3ac03ac,0x40c040c,0x46c046c,0x4cc04cc,
0x1cc01cc,0x22c022c,0x28c028c,0x2ec02ec,0x22c01cc,0x28c028c,0x2ec028c,0x34c034c,0x1cc01cc,0x22c022c,0x28c028c,0x2ec02ec,0x22c022c,0x28c028c,0x2ec02ec,0x34c034c,
0x4c004c,0xac00ac,0x10c010c,0x16c016c,0xac004c,0x10c010c,0x16c010c,0x1cc01cc,0x4c004c,0xac00ac,0x10c010c,0x16c016c,0xac00ac,0x10c010c,0x16c016c,0x1cc01cc,
0xac80ac8,0xb280b28,0xb880b88,0xbe80be8,0xb280ac8,0xb880b88,0xbe80b88,0x4c004c,0xac80ac8,0xb280b28,0xb880b88,0xbe80be8,0xb280b28,0xb880b88,0xbe80be8,0x4c004c,
0x9480948,0x9a809a8,0xa080a08,0xa680a68,0x9a80948,0xa080a08,0xa680a08,0xac80ac8,0x9480948,0x9a809a8,0xa080a08,0xa680a68,0x9a809a8,0xa080a08,0xa680a68,0xac80ac8,
0x7c807c8,0x8280828,0x8880888,0x8e808e8,0x82807c8,0x8880888,0x8e80888,0x9480948,0x7c807c8,0x8280828,0x8880888,0x8e808e8,0x8280828,0x8880888,0x8e808e8,0x9480948,
0x6480648,0x6a806a8,0x7080708,0x7680768,0x6a80648,0x7080708,0x7680708,0x7c807c8,0x6480648,0x6a806a8,0x7080708,0x7680768,0x6a806a8,0x7080708,0x7680768,0x7c807c8,
0x4c804c8,0x5280528,0x5880588,0x5e805e8,0x52804c8,0x5880588,0x5e80588,0x6480648,0x4c804c8,0x5280528,0x5880588,0x5e805e8,0x5280528,0x5880588,0x5e805e8,0x6480648,
0x3480348,0x3a803a8,0x4080408,0x4680468,0x3a80348,0x4080408,0x4680408,0x4c804c8,0x3480348,0x3a803a8,0x4080408,0x4680468,0x3a803a8,0x4080408,0x4680468,0x4c804c8,
0x1c801c8,0x2280228,0x2880288,0x2e802e8,0x22801c8,0x2880288,0x2e80288,0x3480348,0x1c801c8,0x2280228,0x2880288,0x2e802e8,0x2280228,0x2880288,0x2e802e8,0x3480348,
0x480048,0xa800a8,0x1080108,0x1680168,0xa80048,0x1080108,0x1680108,0x1c801c8,0x480048,0xa800a8,0x1080108,0x1680168,0xa800a8,0x1080108,0x1680168,0x1c801c8,
0xac40ac4,0xb240b24,0xb840b84,0xbe40be4,0xb240ac4,0xb840b84,0xbe40b84,0x480048,0xac40ac4,0xb240b24,0xb840b84,0xbe40be4,0xb240b24,0xb840b84,0xbe40be4,0x480048,
0x9440944,0x9a409a4,0xa040a04,0xa640a64,0x9a40944,0xa040a04,0xa640a04,0xac40ac4,0x9440944,0x9a409a4,0xa040a04,0xa640a64,0x9a409a4,0xa040a04,0xa640a64,0xac40ac4,
0x7c407c4,0x8240824,0x8840884,0x8e408e4,0x82407c4,0x8840884,0x8e40884,0x9440944,0x7c407c4,0x8240824,0x8840884,0x8e408e4,0x8240824,0x8840884,0x8e408e4,0x9440944,
0x6440644,0x6a406a4,0x7040704,0x7640764,0x6a40644,0x7040704,0x7640704,0x7c407c4,0x6440644,0x6a406a4,0x7040704,0x7640764,0x6a406a4,0x7040704,0x7640764,0x7c407c4,
0x4c404c4,0x5240524,0x5840584,0x5e405e4,0x52404c4,0x5840584,0x5e40584,0x6440644,0x4c404c4,0x5240524,0x5840584,0x5e405e4,0x5240524,0x5840584,0x5e405e4,0x6440644,
0x3440344,0x3a403a4,0x4040404,0x4640464,0x3a40344,0x4040404,0x4640404,0x4c404c4,0x3440344,0x3a403a4,0x4040404,0x4640464,0x3a403a4,0x4040404,0x4640464,0x4c404c4,
0x1c401c4,0x2240224,0x2840284,0x2e402e4,0x22401c4,0x2840284,0x2e40284,0x3440344,0x1c401c4,0x2240224,0x2840284,0x2e402e4,0x2240224,0x2840284,0x2e402e4,0x3440344,
0x440044,0xa400a4,0x1040104,0x1640164,0xa40044,0x1040104,0x1640104,0x1c401c4,0x440044,0xa400a4,0x1040104,0x1640164,0xa400a4,0x1040104,0x1640164,0x1c401c4,
0xac00ac0,0xb200b20,0xb800b80,0xbe00be0,0xb200ac0,0xb800b80,0xbe00b80,0x440044,0xac00ac0,0xb200b20,0xb800b80,0xbe00be0,0xb200b20,0xb800b80,0xbe00be0,0x440044,
0x9400940,0x9a009a0,0xa000a00,0xa600a60,0x9a00940,0xa000a00,0xa600a00,0xac00ac0,0x9400940,0x9a009a0,0xa000a00,0xa600a60,0x9a009a0,0xa000a00,0xa600a60,0xac00ac0,
0x7c007c0,0x8200820,0x8800880,0x8e008e0,0x82007c0,0x8800880,0x8e00880,0x9400940,0x7c007c0,0x8200820,0x8800880,0x8e008e0,0x8200820,0x8800880,0x8e008e0,0x9400940,
0x6400640,0x6a006a0,0x7000700,0x7600760,0x6a00640,0x7000700,0x7600700,0x7c007c0,0x6400640,0x6a006a0,0x7000700,0x7600760,0x6a006a0,0x7000700,0x7600760,0x7c007c0,
0x4c004c0,0x5200520,0x5800580,0x5e005e0,0x52004c0,0x5800580,0x5e00580,0x6400640,0x4c004c0,0x5200520,0x5800580,0x5e005e0,0x5200520,0x5800580,0x5e005e0,0x6400640,
0x3400340,0x3a003a0,0x4000400,0x4600460,0x3a00340,0x4000400,0x4600400,0x4c004c0,0x3400340,0x3a003a0,0x4000400,0x4600460,0x3a003a0,0x4000400,0x4600460,0x4c004c0,
0x1c001c0,0x2200220,0x2800280,0x2e002e0,0x22001c0,0x2800280,0x2e00280,0x3400340,0x1c001c0,0x2200220,0x2800280,0x2e002e0,0x2200220,0x2800280,0x2e002e0,0x3400340,
0x400040,0xa000a0,0x1000100,0x1600160,0xa00040,0x1000100,0x1600100,0x1c001c0,0x400040,0xa000a0,0x1000100,0x1600160,0xa000a0,0x1000100,0x1600160,0x1c001c0,
0x30003000,0x30003000,0x30003000,0x30003000,0x30003000,0x30003000,0x30003000,0x30003000,0x0,0x0,0x0,0x0,0x0,0x0,0x0,0x0,
0x30003000,0x30003000,0x30003000,0x30003000,0x30003000,0x30003000,0x30003000,0x30003000,0x0,0x0,0x0,0x0,0x0,0x0,0x0,0x0,
0x2a1f2da8,0xaf64ada8,0xaa1fada8,0x2f642da8,0x2f643000,0xaa1f0000,0xaf64b000,0x2a1f8000,0x2f642da8,0x2a1f2da8,0xaf64ada8,0xaa1fada8,0x2a1f0000,0x2f643000,0xaa1f0000,0xaf64b000,
0x263e2c72,0xafd9aea7,0xa63eac72,0x2fd92ea7,0x2ea72fd9,0xac72a63e,0xaea7afd9,0x2c72263e,0x2fd92ea7,0x263e2c72,0xafd9aea7,0xa63eac72,0x2c72263e,0x2ea72fd9,0xac72a63e,0xaea7afd9,
0x2da80000,0xada80000,0x2da88000,0xada80000,0x2da83000,0xada8b000,0x2da83000,0xada8b000,0x2da83000,0xada8b000,0x2da83000,0xada8b000,0xada80000,0x2da88000,0xada80000,0x2da88000,
0x2f642a1f,0xaf64aa1f,0x2f642a1f,0xaf64aa1f,0x2a1f2f64,0xaa1faf64,0x2a1f2f64,0xaa1faf64,0x2a1f2f64,0xaa1faf64,0x2a1f2f64,0xaa1faf64,0xaf64aa1f,0x2f642a1f,0xaf64aa1f,0x2f642a1f,
0xaa1f2da8,0x2f642da8,0x2a1fada8,0xaf64ada8,0x2f640000,0xaa1fb000,0xaf640000,0x2a1f3000,0xaf64ada8,0xaa1f2da8,0x2f642da8,0x2a1fada8,0x2a1f3000,0x2f648000,0xaa1fb000,0xaf640000,
0xaea7263e,0x2c722fd9,0x2ea7a63e,0xac72afd9,0x2fd92c72,0x263eaea7,0xafd9ac72,0xa63e2ea7,0xac72afd9,0xaea7263e,0x2c722fd9,0x2ea7a63e,0xa63e2ea7,0x2fd92c72,0x263eaea7,0xafd9ac72,
0xada82da8,0xada82da8,0xada82da8,0xada82da8,0x2da8ada8,0x2da8ada8,0x2da8ada8,0x2da8ada8,0x2da82da8,0x2da82da8,0x2da82da8,0x2da82da8,0xada8ada8,0xada8ada8,0xada8ada8,0xada8ada8,
0x3000,0x3000,0x3000,0x80003000,0x8000b000,0x8000b000,0x8000b000,0x8000b000,0x30000000,0x30008000,0x30008000,0x30008000,0xb0000000,0xb0000000,0xb0000000,0xb0000000,
0x2ea7263e,0xac722fd9,0xaea7a63e,0x2c72afd9,0xafd92c72,0xa63eaea7,0x2fd9ac72,0x263e2ea7,0x2c72afd9,0x2ea7263e,0xac722fd9,0xaea7a63e,0x263e2ea7,0xafd92c72,0xa63eaea7,0x2fd9ac72,
0x2f64ada8,0x2a1f2da8,0xaf642da8,0xaa1fada8,0xaa1f3000,0xaf640000,0x2a1fb000,0x2f648000,0xaa1fada8,0x2f64ada8,0x2a1f2da8,0xaf642da8,0x2f640000,0xaa1f3000,0xaf640000,0x2a1fb000,
0xaa1f2f64,0x2a1faf64,0xaa1f2f64,0x2a1faf64,0x2f64aa1f,0xaf642a1f,0x2f64aa1f,0xaf642a1f,0xaf642a1f,0x2f64aa1f,0xaf642a1f,0x2f64aa1f,0xaa1f2f64,0x2a1faf64,0xaa1f2f64,0x2a1faf64,
0x2da80000,0xada80000,0x2da88000,0xada80000,0x2da8b000,0xada83000,0x2da8b000,0xada83000,0xada83000,0x2da8b000,0xada83000,0x2da8b000,0x2da88000,0xada80000,0x2da88000,0xada88000,
0xa63e2c72,0x2fd9aea7,0x263eac72,0xafd92ea7,0xaea72fd9,0x2c72a63e,0x2ea7afd9,0xac72263e,0xafd92ea7,0xa63e2c72,0x2fd9aea7,0x263eac72,0xac72263e,0xaea72fd9,0x2c72a63e,0x2ea7afd9,
0x2f64ada8,0x2a1fada8,0xaf642da8,0xaa1f2da8,0x2a1f0000,0x2f64b000,0xaa1f0000,0xaf643000,0xaa1f2da8,0x2f64ada8,0x2a1fada8,0xaf642da8,0xaf643000,0x2a1f8000,0x2f64b000,0xaa1f8000,
0xb0003000,0xb0003000,0xb0003000,0xb0003000,0xb0003000,0xb0003000,0xb0003000,0xb0003000,0x0,0x8000,0x8000,0x80008000,0x8000,0x8000,0x8000,0x8000,
0x80000000,0x80000000,0x80008000,0x80008000,0x80000000,0x80008000,0x80008000,0x80008000,0xb0003000,0xb0003000,0xb0003000,0xb0003000,0xb0003000,0xb0003000,0xb0003000,0xb0003000,
0xaa1f2da8,0x2f64ada8,0x2a1fada8,0xaf642da8,0xaf643000,0x2a1f0000,0x2f64b000,0xaa1f8000,0xaf642da8,0xaa1f2da8,0x2f64ada8,0x2a1fada8,0xaa1f0000,0xaf643000,0x2a1f0000,0x2f64b000,
0x2fd9aea7,0x263eac72,0xafd92ea7,0xa63e2c72,0x2c72a63e,0x2ea7afd9,0xac72263e,0xaea72fd9,0xa63e2c72,0x2fd9aea7,0x263eac72,0xafd92ea7,0xaea72fd9,0x2c72a63e,0x2ea7afd9,0xac72263e,
0xada80000,0x2da80000,0xada88000,0x2da80000,0xada83000,0x2da8b000,0xada83000,0x2da8b000,0xada83000,0x2da8b000,0xada83000,0x2da8b000,0x2da80000,0xada88000,0x2da88000,0xada88000,
0xaa1f2f64,0x2a1faf64,0xaa1f2f64,0x2a1faf64,0x2f64aa1f,0xaf642a1f,0x2f64aa1f,0xaf642a1f,0x2f64aa1f,0xaf642a1f,0x2f64aa1f,0xaf642a1f,0x2a1faf64,0xaa1f2f64,0x2a1faf64,0xaa1f2f64,
0x2a1f2da8,0xaf642da8,0xaa1fada8,0x2f64ada8,0xaf640000,0x2a1fb000,0x2f640000,0xaa1f3000,0x2f64ada8,0x2a1f2da8,0xaf642da8,0xaa1fada8,0xaa1f3000,0xaf648000,0x2a1fb000,0x2f640000,
0x2c72afd9,0x2ea7263e,0xac722fd9,0xaea7a63e,0x263e2ea7,0xafd92c72,0xa63eaea7,0x2fd9ac72,0xaea7a63e,0x2c72afd9,0x2ea7263e,0xac722fd9,0x2fd9ac72,0x263e2ea7,0xafd92c72,0xa63eaea7,
0x2da8ada8,0x2da8ada8,0x2da8ada8,0x2da8ada8,0xada82da8,0xada82da8,0xada82da8,0xada82da8,0x2da82da8,0x2da82da8,0x2da82da8,0x2da82da8,0xada8ada8,0xada8ada8,0xada8ada8,0xada8ada8,
0x80003000,0x80003000,0x80003000,0x3000,0xb000,0x8000b000,0xb000,0xb000,0xb0000000,0xb0008000,0xb0008000,0xb0008000,0x30000000,0x30000000,0x30000000,0x30008000,
0x2c722fd9,0x2ea7a63e,0xac72afd9,0xaea7263e,0x263eaea7,0xafd9ac72,0xa63e2ea7,0x2fd92c72,0xaea7263e,0x2c722fd9,0x2ea7a63e,0xac72afd9,0x2fd92c72,0x263eaea7,0xafd9ac72,0xa63e2ea7,
0xaf64ada8,0xaa1f2da8,0x2f642da8,0x2a1fada8,0x2a1f3000,0x2f648000,0xaa1fb000,0xaf648000,0x2a1fada8,0xaf64ada8,0xaa1f2da8,0x2f642da8,0xaf640000,0x2a1f3000,0x2f648000,0xaa1fb000,
0x2f642a1f,0xaf64aa1f,0x2f642a1f,0xaf64aa1f,0x2a1f2f64,0xaa1faf64,0x2a1f2f64,0xaa1faf64,0xaa1faf64,0x2a1f2f64,0xaa1faf64,0x2a1f2f64,0x2f642a1f,0xaf64aa1f,0x2f642a1f,0xaf64aa1f,
0xada80000,0x2da80000,0xada88000,0x2da88000,0xada8b000,0x2da83000,0xada8b000,0x2da83000,0x2da83000,0xada8b000,0x2da83000,0xada8b000,0xada88000,0x2da88000,0xada88000,0x2da80000,
0x2fd92ea7,0x263e2c72,0xafd9aea7,0xa63eac72,0x2c72263e,0x2ea72fd9,0xac72a63e,0xaea7afd9,0xa63eac72,0x2fd92ea7,0x263e2c72,0xafd9aea7,0xaea7afd9,0x2c72263e,0x2ea72fd9,0xac72a63e,
0xaf64ada8,0xaa1fada8,0x2f642da8,0x2a1f2da8,0xaa1f0000,0xaf64b000,0x2a1f0000,0x2f643000,0x2a1f2da8,0xaf64ada8,0xaa1fada8,0x2f642da8,0x2f643000,0xaa1f8000,0xaf64b000,0x2a1f0000,
0x80008000,0x80008000,0x80008000,0x80008000,0x80008000,0x80008000,0x80008000,0x80008000,0x30003000,0x30003000,0x30003000,0x30003000,0x30003000,0x30003000,0x30003000,0x30003000,
0x80008000,0x80008000,0x80008000,0x80008000,0x80008000,0x80008000,0x80008000,0x80008000,0x30003000,0x30003000,0x30003000,0x30003000,0x30003000,0x30003000,0x30003000,0x30003000,
0xaf64ada8,0xaa1fada8,0x2f642da8,0x2a1f2da8,0xaa1f8000,0xaf64b000,0x2a1f8000,0x2f643000,0x2a1f2da8,0xaf64ada8,0xaa1fada8,0x2f642da8,0x2f643000,0xaa1f0000,0xaf64b000,0x2a1f8000,
0xafd9aea7,0xa63eac72,0x2fd92ea7,0x263e2c72,0xac72a63e,0xaea7afd9,0x2c72263e,0x2ea72fd9,0x263e2c72,0xafd9aea7,0xa63eac72,0x2fd92ea7,0x2ea72fd9,0xac72a63e,0xaea7afd9,0x2c72263e,
0x2da83000,0xada8b000,0x2da83000,0xada8b000,0xada80000,0x2da88000,0xada80000,0x2da88000,0xada88000,0x2da88000,0xada80000,0x2da88000,0xada8b000,0x2da83000,0xada8b000,0x2da83000,
0x2a1f2f64,0xaa1faf64,0x2a1f2f64,0xaa1faf64,0xaf64aa1f,0x2f642a1f,0xaf64aa1f,0x2f642a1f,0xaf64aa1f,0x2f642a1f,0xaf64aa1f,0x2f642a1f,0xaa1faf64,0x2a1f2f64,0xaa1faf64,0x2a1f2f64,
0xaf64ada8,0xaa1f2da8,0x2f642da8,0x2a1fada8,0x2a1f3000,0x2f648000,0xaa1fb000,0xaf640000,0x2a1fada8,0xaf64ada8,0xaa1f2da8,0x2f642da8,0xaf648000,0x2a1f3000,0x2f648000,0xaa1fb000,
0xac72afd9,0xaea7263e,0x2c722fd9,0x2ea7a63e,0xa63e2ea7,0x2fd92c72,0x263eaea7,0xafd9ac72,0x2ea7a63e,0xac72afd9,0xaea7263e,0x2c722fd9,0xafd9ac72,0xa63e2ea7,0x2fd92c72,0x263eaea7,
0xada8ada8,0xada8ada8,0xada8ada8,0xada8ada8,0x2da82da8,0x2da82da8,0x2da82da8,0x2da82da8,0xada82da8,0xada82da8,0xada82da8,0xada82da8,0x2da8ada8,0x2da8ada8,0x2da8ada8,0x2da8ada8,
0xb0008000,0xb0000000,0xb0000000,0xb0000000,0x30008000,0x30008000,0x30008000,0x30008000,0x3000,0x3000,0x3000,0x80003000,0x8000b000,0x8000b000,0x8000b000,0x8000b000,
0xac722fd9,0xaea7a63e,0x2c72afd9,0x2ea7263e,0xa63eaea7,0x2fd9ac72,0x263e2ea7,0xafd92c72,0x2ea7263e,0xac722fd9,0xaea7a63e,0x2c72afd9,0xafd92c72,0xa63eaea7,0x2fd9ac72,0x263e2ea7,
0x2a1f2da8,0xaf642da8,0xaa1fada8,0x2f64ada8,0xaf648000,0x2a1fb000,0x2f648000,0xaa1f3000,0x2f64ada8,0x2a1f2da8,0xaf642da8,0xaa1fada8,0xaa1f3000,0xaf640000,0x2a1fb000,0x2f648000,
0xaf642a1f,0x2f64aa1f,0xaf642a1f,0x2f64aa1f,0xaa1f2f64,0x2a1faf64,0xaa1f2f64,0x2a1faf64,0x2a1faf64,0xaa1f2f64,0x2a1faf64,0xaa1f2f64,0xaf642a1f,0x2f64aa1f,0xaf642a1f,0x2f64aa1f,
0xada83000,0x2da8b000,0xada83000,0x2da8b000,0x2da88000,0xada80000,0x2da88000,0xada88000,0xada88000,0x2da88000,0xada80000,0x2da88000,0xada83000,0x2da8b000,0xada83000,0x2da8b000,
0xafd92ea7,0xa63e2c72,0x2fd9aea7,0x263eac72,0xac72263e,0xaea72fd9,0x2c72a63e,0x2ea7afd9,0x263eac72,0xafd92ea7,0xa63e2c72,0x2fd9aea7,0x2ea7afd9,0xac72263e,0xaea72fd9,0x2c72a63e,
0xaa1f2da8,0x2f64ada8,0x2a1fada8,0xaf642da8,0xaf643000,0x2a1f8000,0x2f64b000,0xaa1f8000,0xaf642da8,0xaa1f2da8,0x2f64ada8,0x2a1fada8,0xaa1f8000,0xaf643000,0x2a1f8000,0x2f64b000,
0x80008000,0x80000000,0x80000000,0x0,0x80000000,0x80000000,0x80000000,0x80000000,0xb0003000,0xb0003000,0xb0003000,0xb0003000,0xb0003000,0xb0003000,0xb0003000,0xb0003000,
0x3000b000,0x3000b000,0x3000b000,0x3000b000,0x3000b000,0x3000b000,0x3000b000,0x3000b000,0x80000000,0x80000000,0x80008000,0x80008000,0x80000000,0x80008000,0x80008000,0x80008000,
0x2f64ada8,0x2a1fada8,0xaf642da8,0xaa1f2da8,0x2a1f8000,0x2f64b000,0xaa1f8000,0xaf643000,0xaa1f2da8,0x2f64ada8,0x2a1fada8,0xaf642da8,0xaf643000,0x2a1f0000,0x2f64b000,0xaa1f8000,
0x263eac72,0xafd92ea7,0xa63e2c72,0x2fd9aea7,0x2ea7afd9,0xac72263e,0xaea72fd9,0x2c72a63e,0x2fd9aea7,0x263eac72,0xafd92ea7,0xa63e2c72,0x2c72a63e,0x2ea7afd9,0xac72263e,0xaea72fd9,
0xada83000,0x2da8b000,0xada83000,0x2da8b000,0x2da80000,0xada88000,0x2da88000,0xada88000,0x2da88000,0xada88000,0x2da80000,0xada88000,0x2da8b000,0xada83000,0x2da8b000,0xada83000,
0x2f64aa1f,0xaf642a1f,0x2f64aa1f,0xaf642a1f,0x2a1faf64,0xaa1f2f64,0x2a1faf64,0xaa1f2f64,0x2a1faf64,0xaa1f2f64,0x2a1faf64,0xaa1f2f64,0xaf642a1f,0x2f64aa1f,0xaf642a1f,0x2f64aa1f,
0x2f64ada8,0x2a1f2da8,0xaf642da8,0xaa1fada8,0xaa1f3000,0xaf648000,0x2a1fb000,0x2f640000,0xaa1fada8,0x2f64ada8,0x2a1f2da8,0xaf642da8,0x2f648000,0xaa1f3000,0xaf648000,0x2a1fb000,
0xaea7a63e,0x2c72afd9,0x2ea7263e,0xac722fd9,0x2fd9ac72,0x263e2ea7,0xafd92c72,0xa63eaea7,0xac722fd9,0xaea7a63e,0x2c72afd9,0x2ea7263e,0xa63eaea7,0x2fd9ac72,0x263e2ea7,0xafd92c72,
0xada8ada8,0xada8ada8,0xada8ada8,0xada8ada8,0x2da82da8,0x2da82da8,0x2da82da8,0x2da82da8,0x2da8ada8,0x2da8ada8,0x2da8ada8,0x2da8ada8,0xada82da8,0xada82da8,0xada82da8,0xada82da8,
0x30008000,0x30000000,0x30000000,0x30000000,0xb0008000,0xb0008000,0xb0008000,0xb0000000,0x80003000,0x80003000,0x80003000,0x3000,0xb000,0x8000b000,0xb000,0xb000,
0x2ea7a63e,0xac72afd9,0xaea7263e,0x2c722fd9,0xafd9ac72,0xa63e2ea7,0x2fd92c72,0x263eaea7,0x2c722fd9,0x2ea7a63e,0xac72afd9,0xaea7263e,0x263eaea7,0xafd9ac72,0xa63e2ea7,0x2fd92c72,
0xaa1f2da8,0x2f642da8,0x2a1fada8,0xaf64ada8,0x2f648000,0xaa1fb000,0xaf640000,0x2a1f3000,0xaf64ada8,0xaa1f2da8,0x2f642da8,0x2a1fada8,0x2a1f3000,0x2f648000,0xaa1fb000,0xaf648000,
0xaa1faf64,0x2a1f2f64,0xaa1faf64,0x2a1f2f64,0x2f642a1f,0xaf64aa1f,0x2f642a1f,0xaf64aa1f,0xaf64aa1f,0x2f642a1f,0xaf64aa1f,0x2f642a1f,0xaa1faf64,0x2a1f2f64,0xaa1faf64,0x2a1f2f64,
0x2da83000,0xada8b000,0x2da83000,0xada8b000,0xada88000,0x2da88000,0xada88000,0x2da80000,0x2da88000,0xada88000,0x2da80000,0xada80000,0x2da83000,0xada8b000,0x2da83000,0xada8b000,
0xa63eac72,0x2fd92ea7,0x263e2c72,0xafd9aea7,0xaea7afd9,0x2c72263e,0x2ea72fd9,0xac72a63e,0xafd9aea7,0xa63eac72,0x2fd92ea7,0x263e2c72,0xac72a63e,0xaea7afd9,0x2c72263e,0x2ea72fd9,
0x2a1f2da8,0xaf64ada8,0xaa1fada8,0x2f642da8,0x2f643000,0xaa1f8000,0xaf64b000,0x2a1f0000,0x2f642da8,0x2a1f2da8,0xaf64ada8,0xaa1fada8,0x2a1f8000,0x2f643000,0xaa1f8000,0xaf64b000,
0x3c003c00,0x3c003c00,0x3c003c00,0x3c003c00,0x3c003c00,0x3c003c00,0x3c003c00,0x3c003c00,0x80008000,0x80008000,0x80008000,0x80008000,0x80008000,0x80008000,0x80008000,0x80008000,
0x3bd93c00,0x3aa73b64,0x387239a8,0x323e361f,0xb23e0000,0xb872b61f,0xbaa7b9a8,0xbbd9bb64,0xb23e8000,0xb872b61f,0xbaa7b9a8,0xbbd9bb64,0xbbd9bc00,0xbaa7bb64,0xb872b9a8,0xb23eb61f,
0xbb64bc00,0xb61fb9a8,0x361f8000,0x3b6439a8,0x3b643c00,0x361f39a8,0xb61f0000,0xbb64b9a8,0x361f8000,0x3b6439a8,0x3b643c00,0x361f39a8,0xb61f8000,0xbb64b9a8,0xbb64bc00,0xb61fb9a8,
0x38728000,0x3bd93b64,0x323e39a8,0xbaa7b61f,0x3aa73c00,0xb23e361f,0xbbd9b9a8,0xb872bb64,0x3aa73c00,0xb23e361f,0xbbd9b9a8,0xb872bb64,0xb8728000,0xbbd9bb64,0xb23eb9a8,0x3aa7361f,
0xbc008000,0x3c008000,0xbc000000,0x3c008000,0xbc000000,0x3c008000,0xbc000000,0x3c008000,0x3c00,0x8000bc00,0x3c00,0x8000bc00,0x3c00,0x8000bc00,0x80003c00,0x8000bc00,
0xbbd98000,0x3aa7361f,0xb872b9a8,0x323e3b64,0x323ebc00,0xb8723b64,0x3aa7b9a8,0xbbd9361f,0xb23e3c00,0x3872bb64,0xbaa739a8,0x3bd9b61f,0xbbd90000,0x3aa7361f,0xb872b9a8,0x323e3b64,
0x3b648000,0xb61fb9a8,0xb61f3c00,0x3b64b9a8,0xbb648000,0x361f39a8,0x361fbc00,0xbb6439a8,0x361fbc00,0xbb6439a8,0x3b648000,0xb61fb9a8,0xb61f3c00,0x3b64b9a8,0xbb640000,0x361f39a8,
0xb8723c00,0x3bd9b61f,0xb23eb9a8,0xbaa73b64,0xbaa78000,0xb23e3b64,0x3bd9b9a8,0xb872b61f,0x3aa78000,0x323ebb64,0xbbd939a8,0x3872361f,0xb8723c00,0x3bd9b61f,0xb23eb9a8,0xbaa73b64,
0xbbd93c00,0xbaa73b64,0xb87239a8,0xb23e361f,0x323e8000,0x3872b61f,0x3aa7b9a8,0x3bd9bb64,0x323e8000,0x3872b61f,0x3aa7b9a8,0x3bd9bb64,0x3bd9bc00,0x3aa7bb64,0x3872b9a8,0x323eb61f,
0xbc003c00,0xbc003c00,0xbc003c00,0xbc003c00,0xbc003c00,0xbc003c00,0xbc003c00,0xbc003c00,0x80008000,0x80000000,0x80000000,0x80000000,0x80000000,0x80000000,0x0,0x80000000,
0xb8728000,0xbbd93b64,0xb23e39a8,0x3aa7b61f,0xbaa73c00,0x323e361f,0x3bd9b9a8,0x3872bb64,0xbaa73c00,0x323e361f,0x3bd9b9a8,0x3872bb64,0x38728000,0x3bd9bb64,0x323eb9a8,0xbaa7361f,
0x3b64bc00,0x361fb9a8,0xb61f8000,0xbb6439a8,0xbb643c00,0xb61f39a8,0x361f0000,0x3b64b9a8,0xb61f8000,0xbb6439a8,0xbb643c00,0xb61f39a8,0x361f8000,0x3b64b9a8,0x3b64bc00,0x361fb9a8,
0x3bd98000,0xbaa7361f,0x3872b9a8,0xb23e3b64,0xb23ebc00,0x38723b64,0xbaa7b9a8,0x3bd9361f,0x323e3c00,0xb872bb64,0x3aa739a8,0xbbd9b61f,0x3bd98000,0xbaa7361f,0x3872b9a8,0xb23e3b64,
0x3c008000,0xbc008000,0x3c000000,0xbc008000,0x3c000000,0xbc008000,0x3c000000,0xbc000000,0x80003c00,0xbc00,0x80003c00,0x8000bc00,0x80003c00,0xbc00,0x80003c00,0xbc00,
0x38723c00,0xbbd9b61f,0x323eb9a8,0x3aa73b64,0x3aa78000,0x323e3b64,0xbbd9b9a8,0x3872b61f,0xbaa78000,0xb23ebb64,0x3bd939a8,0xb872361f,0x38723c00,0xbbd9b61f,0x323eb9a8,0x3aa73b64,
0xbb640000,0x361fb9a8,0x361f3c00,0xbb64b9a8,0x3b648000,0xb61f39a8,0xb61fbc00,0x3b6439a8,0xb61fbc00,0x3b6439a8,0xbb640000,0x361fb9a8,0x361f3c00,0xbb64b9a8,0x3b648000,0xb61f39a8,
0x39a83c00,0xb9a80000,0xb9a8bc00,0x39a88000,0x39a83c00,0xb9a80000,0xb9a8bc00,0x39a88000,0xb9a88000,0xb9a8bc00,0x39a88000,0x39a83c00,0xb9a80000,0xb9a8bc00,0x39a88000,0x39a83c00,
0x38723c00,0xbbd9b61f,0x323eb9a8,0x3aa73b64,0xbaa70000,0xb23ebb64,0x3bd939a8,0xb872361f,0xbaa78000,0xb23ebb64,0x3bd939a8,0xb872361f,0xb872bc00,0x3bd9361f,0xb23e39a8,0xbaa7bb64,
0xb61fbc00,0x3b6439a8,0xbb640000,0x361fb9a8,0x361f3c00,0xbb64b9a8,0x3b648000,0xb61f39a8,0x3b648000,0xb61f39a8,0xb61fbc00,0x3b6439a8,0xbb648000,0x361fb9a8,0x361f3c00,0xbb64b9a8,
0x3bd98000,0xbaa7361f,0x3872b9a8,0xb23e3b64,0x323e3c00,0xb872bb64,0x3aa739a8,0xbbd9b61f,0x323e3c00,0xb872bb64,0x3aa739a8,0xbbd9b61f,0xbbd98000,0x3aa7b61f,0xb87239a8,0x323ebb64,
0xb9a88000,0xb9a83c00,0x39a88000,0x39a8bc00,0xb9a80000,0xb9a83c00,0x39a88000,0x39a8bc00,0xb9a83c00,0x39a88000,0x39a8bc00,0xb9a80000,0xb9a83c00,0x39a88000,0x39a8bc00,0xb9a88000,
0xb8728000,0xbbd93b64,0xb23e39a8,0x3aa7b61f,0x3aa7bc00,0xb23eb61f,0xbbd939a8,0xb8723b64,0xbaa73c00,0x323e361f,0x3bd9b9a8,0x3872bb64,0xb8728000,0xbbd93b64,0xb23e39a8,0x3aa7b61f,
0x361f8000,0x3b64b9a8,0x3b64bc00,0x361fb9a8,0xb61f8000,0xbb6439a8,0xbb643c00,0xb61f39a8,0x3b64bc00,0x361fb9a8,0xb61f8000,0xbb6439a8,0xbb643c00,0xb61f39a8,0x361f8000,0x3b64b9a8,
0xbbd93c00,0xbaa73b64,0xb87239a8,0xb23e361f,0xb23e8000,0xb872361f,0xbaa739a8,0xbbd93b64,0x323e8000,0x3872b61f,0x3aa7b9a8,0x3bd9bb64,0xbbd93c00,0xbaa73b64,0xb87239a8,0xb23e361f,
0xb8723c00,0x3bd9b61f,0xb23eb9a8,0xbaa73b64,0x3aa78000,0x323ebb64,0xbbd939a8,0x3872361f,0x3aa78000,0x323ebb64,0xbbd939a8,0x3872361f,0x3872bc00,0xbbd9361f,0x323e39a8,0x3aa7bb64,
0xb9a83c00,0x39a80000,0x39a8bc00,0xb9a88000,0xb9a83c00,0x39a88000,0x39a8bc00,0xb9a88000,0x39a88000,0x39a8bc00,0xb9a88000,0xb9a83c00,0x39a80000,0x39a8bc00,0xb9a88000,0xb9a83c00,
0xbbd98000,0x3aa7361f,0xb872b9a8,0x323e3b64,0xb23e3c00,0x3872bb64,0xbaa739a8,0x3bd9b61f,0xb23e3c00,0x3872bb64,0xbaa739a8,0x3bd9b61f,0x3bd98000,0xbaa7b61f,0x387239a8,0xb23ebb64,
0x361fbc00,0xbb6439a8,0x3b640000,0xb61fb9a8,0xb61f3c00,0x3b64b9a8,0xbb648000,0x361f39a8,0xbb648000,0x361f39a8,0x361fbc00,0xbb6439a8,0x3b648000,0xb61fb9a8,0xb61f3c00,0x3b64b9a8,
0x38728000,0x3bd93b64,0x323e39a8,0xbaa7b61f,0xbaa7bc00,0x323eb61f,0x3bd939a8,0x38723b64,0x3aa73c00,0xb23e361f,0xbbd9b9a8,0xb872bb64,0x38728000,0x3bd93b64,0x323e39a8,0xbaa7b61f,
0x39a88000,0x39a83c00,0xb9a88000,0xb9a8bc00,0x39a80000,0x39a83c00,0xb9a80000,0xb9a8bc00,0x39a83c00,0xb9a88000,0xb9a8bc00,0x39a88000,0x39a83c00,0xb9a88000,0xb9a8bc00,0x39a80000,
0x3bd93c00,0x3aa73b64,0x387239a8,0x323e361f,0x323e8000,0x3872361f,0x3aa739a8,0x3bd93b64,0xb23e8000,0xb872b61f,0xbaa7b9a8,0xbbd9bb64,0x3bd93c00,0x3aa73b64,0x387239a8,0x323e361f,
0xb61f8000,0xbb64b9a8,0xbb64bc00,0xb61fb9a8,0x361f8000,0x3b6439a8,0x3b643c00,0x361f39a8,0xbb64bc00,0xb61fb9a8,0x361f0000,0x3b6439a8,0x3b643c00,0x361f39a8,0xb61f8000,0xbb64b9a8,
0x0,0x0,0x0,0x0,0x0,0x0,0x0,0x0,0x3c003c00,0x3c003c00,0x3c003c00,0x3c003c00,0x3c003c00,0x3c003c00,0x3c003c00,0x3c003c00,
0x323e0000,0x3872361f,0x3aa739a8,0x3bd93b64,0x3bd93c00,0x3aa73b64,0x387239a8,0x323e361f,0x3bd93c00,0x3aa73b64,0x387239a8,0x323e361f,0xb23e0000,0xb872b61f,0xbaa7b9a8,0xbbd9bb64,
0xb61f0000,0xbb64b9a8,0xbb64bc00,0xb61fb9a8,0x361f0000,0x3b6439a8,0x3b643c00,0x361f39a8,0xbb64bc00,0xb61fb9a8,0x361f8000,0x3b6439a8,0x3b643c00,0x361f39a8,0xb61f0000,0xbb64b9a8,
0xbaa7bc00,0x323eb61f,0x3bd939a8,0x38723b64,0x38720000,0x3bd93b64,0x323e39a8,0xbaa7b61f,0x38728000,0x3bd93b64,0x323e39a8,0xbaa7b61f,0x3aa73c00,0xb23e361f,0xbbd9b9a8,0xb872bb64,
0x3c00,0x8000bc00,0x3c00,0x8000bc00,0x3c00,0x8000bc00,0x80003c00,0x8000bc00,0x3c000000,0xbc000000,0x3c008000,0xbc000000,0x3c008000,0xbc000000,0x3c008000,0xbc000000,
0xb23e3c00,0x3872bb64,0xbaa739a8,0x3bd9b61f,0xbbd90000,0x3aa7361f,0xb872b9a8,0x323e3b64,0x3bd90000,0xbaa7b61f,0x387239a8,0xb23ebb64,0xb23e3c00,0x3872bb64,0xbaa739a8,0x3bd9b61f,
0x361fbc00,0xbb6439a8,0x3b648000,0xb61fb9a8,0xb61f3c00,0x3b64b9a8,0xbb640000,0x361f39a8,0xbb640000,0x361f39a8,0x361fbc00,0xbb6439a8,0x3b640000,0xb61fb9a8,0xb61f3c00,0x3b64b9a8,
0x3aa78000,0x323ebb64,0xbbd939a8,0x3872361f,0xb8723c00,0x3bd9b61f,0xb23eb9a8,0xbaa73b64,0x3872bc00,0xbbd9361f,0x323e39a8,0x3aa7bb64,0x3aa70000,0x323ebb64,0xbbd939a8,0x3872361f,
0xb23e0000,0xb872361f,0xbaa739a8,0xbbd93b64,0xbbd93c00,0xbaa73b64,0xb87239a8,0xb23e361f,0xbbd93c00,0xbaa73b64,0xb87239a8,0xb23e361f,0x323e8000,0x3872b61f,0x3aa7b9a8,0x3bd9bb64,
0x0,0x8000,0x8000,0x8000,0x8000,0x8000,0x80008000,0x8000,0xbc003c00,0xbc003c00,0xbc003c00,0xbc003c00,0xbc003c00,0xbc003c00,0xbc003c00,0xbc003c00,
0x3aa7bc00,0xb23eb61f,0xbbd939a8,0xb8723b64,0xb8720000,0xbbd93b64,0xb23e39a8,0x3aa7b61f,0xb8728000,0xbbd93b64,0xb23e39a8,0x3aa7b61f,0xbaa73c00,0x323e361f,0x3bd9b9a8,0x3872bb64,
0x361f0000,0x3b64b9a8,0x3b64bc00,0x361fb9a8,0xb61f0000,0xbb6439a8,0xbb643c00,0xb61f39a8,0x3b64bc00,0x361fb9a8,0xb61f8000,0xbb6439a8,0xbb643c00,0xb61f39a8,0x361f0000,0x3b64b9a8,
0x323e3c00,0xb872bb64,0x3aa739a8,0xbbd9b61f,0x3bd98000,0xbaa7361f,0x3872b9a8,0xb23e3b64,0xbbd90000,0x3aa7b61f,0xb87239a8,0x323ebb64,0x323e3c00,0xb872bb64,0x3aa739a8,0xbbd9b61f,
0x80003c00,0xbc00,0x80003c00,0x8000bc00,0x80003c00,0xbc00,0x80003c00,0xbc00,0xbc000000,0x3c000000,0xbc008000,0x3c000000,0xbc008000,0x3c000000,0xbc008000,0x3c008000,
0xbaa78000,0xb23ebb64,0x3bd939a8,0xb872361f,0x38723c00,0xbbd9b61f,0x323eb9a8,0x3aa73b64,0xb872bc00,0x3bd9361f,0xb23e39a8,0xbaa7bb64,0xbaa70000,0xb23ebb64,0x3bd939a8,0xb872361f,
0xb61fbc00,0x3b6439a8,0xbb640000,0x361fb9a8,0x361f3c00,0xbb64b9a8,0x3b648000,0xb61f39a8,0x3b648000,0xb61f39a8,0xb61fbc00,0x3b6439a8,0xbb640000,0x361fb9a8,0x361f3c00,0xbb64b9a8,
0x39a80000,0x39a83c00,0xb9a80000,0xb9a8bc00,0x39a88000,0x39a83c00,0xb9a80000,0xb9a8bc00,0x39a83c00,0xb9a80000,0xb9a8bc00,0x39a88000,0x39a83c00,0xb9a80000,0xb9a8bc00,0x39a88000,
0x3aa70000,0x323e3b64,0xbbd9b9a8,0x3872b61f,0x38723c00,0xbbd9b61f,0x323eb9a8,0x3aa73b64,0x38723c00,0xbbd9b61f,0x323eb9a8,0x3aa73b64,0xbaa70000,0xb23ebb64,0x3bd939a8,0xb872361f,
0xbb640000,0x361fb9a8,0x361f3c00,0xbb64b9a8,0x3b640000,0xb61f39a8,0xb61fbc00,0x3b6439a8,0xb61fbc00,0x3b6439a8,0xbb640000,0x361fb9a8,0x361f3c00,0xbb64b9a8,0x3b648000,0xb61f39a8,
0xb23ebc00,0x38723b64,0xbaa7b9a8,0x3bd9361f,0x3bd90000,0xbaa7361f,0x3872b9a8,0xb23e3b64,0x3bd98000,0xbaa7361f,0x3872b9a8,0xb23e3b64,0x323e3c00,0xb872bb64,0x3aa739a8,0xbbd9b61f,
0xb9a83c00,0x39a88000,0x39a8bc00,0xb9a80000,0xb9a83c00,0x39a88000,0x39a8bc00,0xb9a88000,0x39a80000,0x39a8bc00,0xb9a80000,0xb9a83c00,0x39a88000,0x39a8bc00,0xb9a80000,0xb9a83c00,
0xbaa73c00,0x323e361f,0x3bd9b9a8,0x3872bb64,0xb8728000,0xbbd93b64,0xb23e39a8,0x3aa7b61f,0x38720000,0x3bd9bb64,0x323eb9a8,0xbaa7361f,0xbaa73c00,0x323e361f,0x3bd9b9a8,0x3872bb64,
0x3b64bc00,0x361fb9a8,0xb61f8000,0xbb6439a8,0xbb643c00,0xb61f39a8,0x361f8000,0x3b64b9a8,0xb61f0000,0xbb6439a8,0xbb643c00,0xb61f39a8,0x361f0000,0x3b64b9a8,0x3b64bc00,0x361fb9a8,
0x323e8000,0x3872b61f,0x3aa7b9a8,0x3bd9bb64,0xbbd93c00,0xbaa73b64,0xb87239a8,0xb23e361f,0x3bd9bc00,0x3aa7bb64,0x3872b9a8,0x323eb61f,0x323e0000,0x3872b61f,0x3aa7b9a8,0x3bd9bb64,
0xbaa70000,0xb23e3b64,0x3bd9b9a8,0xb872b61f,0xb8723c00,0x3bd9b61f,0xb23eb9a8,0xbaa73b64,0xb8723c00,0x3bd9b61f,0xb23eb9a8,0xbaa73b64,0x3aa78000,0x323ebb64,0xbbd939a8,0x3872361f,
0xb9a80000,0xb9a83c00,0x39a80000,0x39a8bc00,0xb9a88000,0xb9a83c00,0x39a80000,0x39a8bc00,0xb9a83c00,0x39a80000,0x39a8bc00,0xb9a88000,0xb9a83c00,0x39a88000,0x39a8bc00,0xb9a88000,
0x323ebc00,0xb8723b64,0x3aa7b9a8,0xbbd9361f,0xbbd90000,0x3aa7361f,0xb872b9a8,0x323e3b64,0xbbd98000,0x3aa7361f,0xb872b9a8,0x323e3b64,0xb23e3c00,0x3872bb64,0xbaa739a8,0x3bd9b61f,
0x3b640000,0xb61fb9a8,0xb61f3c00,0x3b64b9a8,0xbb640000,0x361f39a8,0x361fbc00,0xbb6439a8,0x361fbc00,0xbb6439a8,0x3b640000,0xb61fb9a8,0xb61f3c00,0x3b64b9a8,0xbb648000,0x361f39a8,
0x3aa73c00,0xb23e361f,0xbbd9b9a8,0xb872bb64,0x38728000,0x3bd93b64,0x323e39a8,0xbaa7b61f,0xb8720000,0xbbd9bb64,0xb23eb9a8,0x3aa7361f,0x3aa73c00,0xb23e361f,0xbbd9b9a8,0xb872bb64,
0x39a83c00,0xb9a88000,0xb9a8bc00,0x39a88000,0x39a83c00,0xb9a88000,0xb9a8bc00,0x39a80000,0xb9a80000,0xb9a8bc00,0x39a80000,0x39a83c00,0xb9a88000,0xb9a8bc00,0x39a88000,0x39a83c00,
0xb23e8000,0xb872b61f,0xbaa7b9a8,0xbbd9bb64,0x3bd93c00,0x3aa73b64,0x387239a8,0x323e361f,0xbbd9bc00,0xbaa7bb64,0xb872b9a8,0xb23eb61f,0xb23e0000,0xb872b61f,0xbaa7b9a8,0xbbd9bb64,
0xbb64bc00,0xb61fb9a8,0x361f0000,0x3b6439a8,0x3b643c00,0x361f39a8,0xb61f8000,0xbb64b9a8,0x361f0000,0x3b6439a8,0x3b643c00,0x361f39a8,0xb61f0000,0xbb64b9a8,0xbb64bc00,0xb61fb9a8,
};
__device__ __align__(1024) bf16 g_x1T[DM * XP];
__device__ __align__(1024) bf16 g_x2T[DM * XP];
__device__ __align__(1024) float g_sums[2][2][SEQ];

#define TS_DECL
#define TS_ARG
#define TS_PASS
#define TS(i)
#define TSX(row, i)
#define TS_BEGIN
#define TS_END(slot)

__device__ __align__(1024) uint32_t g_keo[DM / 2][2048];
__device__ __align__(128) uint32_t g_ksc[DM];

struct cplx { float r, i; };
__device__ __forceinline__ cplx cmul(cplx a, cplx b) {
    cplx o;
    o.r = fmaf(a.r, b.r, -a.i * b.i);
    o.i = fmaf(a.r, b.i, a.i * b.r);
    return o;
}
__device__ __forceinline__ cplx csq(cplx a) {
    cplx o;
    o.r = fmaf(a.r, a.r, -a.i * a.i);
    o.i = 2.f * a.r * a.i;
    return o;
}
__device__ __forceinline__ cplx cexp_p(float arl, float ai, float p) {
    float mag = ex2(arl * p);
    float ang = ai * p;
    float n = rintf(ang * 0.15915494309189535f);
    float r = fmaf(n, -6.2831854820251465f, ang);
    r = fmaf(n, 1.7484555e-7f, r);
    cplx o;
    o.r = mag * __cosf(r);
    o.i = mag * __sinf(r);
    return o;
}

__device__ __forceinline__ uint32_t pack2h(float lo, float hi) {
    uint32_t r;
    asm("cvt.rn.f16x2.f32 %0, %1, %2;" : "=r"(r) : "f"(hi), "f"(lo));
    return r;
}
__device__ __forceinline__ uint32_t hmul(uint32_t a, uint32_t b) { uint32_t d; asm("mul.rn.f16x2 %0, %1, %2;" : "=r"(d) : "r"(a), "r"(b)); return d; }
__device__ __forceinline__ uint32_t hfma(uint32_t a, uint32_t b, uint32_t c) { uint32_t d; asm("fma.rn.f16x2 %0, %1, %2, %3;" : "=r"(d) : "r"(a), "r"(b), "r"(c)); return d; }
__device__ __forceinline__ uint32_t hfms(uint32_t a, uint32_t b, uint32_t c) {
    uint32_t d;
    asm("{\n.reg .b32 n;\nneg.f16x2 n, %1;\nfma.rn.f16x2 %0, n, %2, %3;\n}" : "=r"(d) : "r"(a), "r"(b), "r"(c));
    return d;
}
__device__ __forceinline__ uint32_t hadd(uint32_t a, uint32_t b) { uint32_t d; asm("add.rn.f16x2 %0, %1, %2;" : "=r"(d) : "r"(a), "r"(b)); return d; }
__device__ __forceinline__ uint32_t hsub(uint32_t a, uint32_t b) { uint32_t d; asm("sub.rn.f16x2 %0, %1, %2;" : "=r"(d) : "r"(a), "r"(b)); return d; }
__device__ __forceinline__ uint4 ldg_tab(int tab, int t) { return __ldg((const uint4*)c_fft + tab * 128 + t); }
__device__ __forceinline__ uint32_t u4(const uint4& v, int i) { return i == 0 ? v.x : i == 1 ? v.y : i == 2 ? v.z : v.w; }
struct cpair { uint32_t r, i; };
__device__ __forceinline__ cpair pmul(cpair p, uint32_t z) {
    const __half2 zv = *reinterpret_cast<const __half2*>(&z), pr = *reinterpret_cast<const __half2*>(&p.r), pi = *reinterpret_cast<const __half2*>(&p.i);
    const __half2 zr = __low2half2(zv), zi = __high2half2(zv);
    const __half2 a = __hfma2(__hneg2(pi), zi, __hmul2(pr, zr)), b = __hfma2(pi, zr, __hmul2(pr, zi));
    return {*reinterpret_cast<const uint32_t*>(&a), *reinterpret_cast<const uint32_t*>(&b)};
}
__device__ __forceinline__ uint32_t packz(cplx z) { return pack2h(z.r, z.i); }
__device__ __forceinline__ void wgmma_kg(float (&d)[24], uint64_t da, uint64_t db, int scale_d) {
    asm volatile("{\n.reg .pred p;\nsetp.ne.b32 p, %26, 0;\n"
                 "wgmma.mma_async.sync.aligned.m64n48k16.f32.f16.f16 "
                 "{%0,%1,%2,%3,%4,%5,%6,%7,%8,%9,%10,%11,%12,%13,%14,%15,%16,%17,%18,%19,%20,%21,%22,%23}, %24, %25, p, 1, 1, 1, 1;\n}\n"
                 : "+f"(d[0]), "+f"(d[1]), "+f"(d[2]), "+f"(d[3]), "+f"(d[4]), "+f"(d[5]), "+f"(d[6]), "+f"(d[7]), "+f"(d[8]), "+f"(d[9]),
                   "+f"(d[10]), "+f"(d[11]), "+f"(d[12]), "+f"(d[13]), "+f"(d[14]), "+f"(d[15]), "+f"(d[16]), "+f"(d[17]), "+f"(d[18]), "+f"(d[19]),
                   "+f"(d[20]), "+f"(d[21]), "+f"(d[22]), "+f"(d[23])
                 : "l"(da), "l"(db), "r"(scale_d));
}

struct SsmParams { const bf16 *lar, *aim, *cre, *cim, *logdt, *dskip; };
constexpr int KG_TABLES = 6 * 16384, KG_IDX = 6 * 3072, KG_DUMP = KG_IDX + 4096;
struct KgShared { uint32_t kmax[5]; };
struct KgParams { uint32_t l[3], a[3], r[3], i[3], dt, ds; };

__device__ __forceinline__ void kgen_load(KgParams& kp, int d0, int warp, int lane, const SsmParams& sp) {
    const int d = d0 + (warp < 8 ? 2 * (warp >> 2) + (warp & 1) : 4), idx = d * (NMODE / 2) + lane;
    const bf16 *pr = (warp & 2) ? sp.cre : sp.lar, *pi = (warp & 2) ? sp.cim : sp.aim;
#pragma unroll
    for (int j = 0; j < 3; j++) {
        kp.l[j] = __ldg((const uint32_t*)sp.lar + idx + 32 * j); kp.a[j] = __ldg((const uint32_t*)sp.aim + idx + 32 * j);
        kp.r[j] = __ldg((const uint32_t*)pr + idx + 32 * j); kp.i[j] = __ldg((const uint32_t*)pi + idx + 32 * j);
    }
    kp.dt = __ldg((const uint16_t*)sp.logdt + d);
    kp.ds = 0;
    if (lane == 0 && warp <= 8 && !(warp & 1)) kp.ds = __ldg((const uint16_t*)sp.dskip + d0 + (warp >> 1));
}

struct KgAnchors { uint32_t v[8]; };
__device__ __forceinline__ KgAnchors kg_anchor_lo(const KgParams& kp, uint32_t sel, float dt) {
    auto B = [&](uint32_t v) { return __uint_as_float(__byte_perm(v, 0u, sel)); };
    const float arl = -rbf(ex2(B(kp.l[0]) * 1.4426950408889634f)) * dt * 1.4426950408889634f, ai = B(kp.a[0]) * dt;
    const cplx z8 = cexp_p(arl, ai, 8.f), z16 = csq(z8), z24 = cmul(z16, z8), z32 = csq(z16), z64 = csq(z32), z128 = csq(z64), z192 = cmul(z128, z64);
    return {{pack2h(1.f, z8.r), pack2h(0.f, z8.i), pack2h(z16.r, z24.r), pack2h(z16.i, z24.i), packz(z32), packz(z64), packz(z128), packz(z192)}};
}
__device__ __forceinline__ KgAnchors kg_anchor_hi(const KgParams& kp, uint32_t sel, float dt, float cs) {
    auto B = [&](uint32_t v) { return __uint_as_float(__byte_perm(v, 0u, sel)); };
    const float arl = -rbf(ex2(B(kp.l[0]) * 1.4426950408889634f)) * dt * 1.4426950408889634f, ai = B(kp.a[0]) * dt;
    const cplx z1 = cexp_p(arl, -ai, 1.f), z2 = csq(z1), z4 = csq(z2), z256 = cexp_p(arl, -ai, 256.f), z512 = csq(z256), z1024 = csq(z512);
    const cplx H0 = {B(kp.r[0]) * cs, -B(kp.i[0]) * cs}, H4 = cmul(H0, z4);
    return {{pack2h(H0.r, H4.r), pack2h(H0.i, H4.i), packz(z1), packz(z2), packz(z256), packz(z512), packz(z1024), 0u}};
}

template <class Hook>
__device__ __forceinline__ void kgen_tables(KgParams& kp, uint32_t scr, uint32_t dump, int warp, int lane, Hook hook TS_ARG) {
    const int wg = warp >> 2, half = warp & 1, sw = lane & 7;
    const bool hi = warp & 2;
    TS(23);
    const float dt = rbf(ex2(bf_lo(kp.dt) * 1.4426950408889634f));
    uint32_t sel = (wg == 2 && half) ? 0x3244u : 0x1044u;
    float cs = 0.f;
    KgAnchors an;
    if (hi) {
        uint32_t m = 0;
#pragma unroll
        for (int j = 0; j < 3; j++) m = __vmaxu2(m, __vmaxu2(kp.r[j] & 0x7FFF7FFFu, kp.i[j] & 0x7FFF7FFFu));
        m = __reduce_max_sync(~0u, max(m << 16, m & 0xFFFF0000u));
        const uint32_t e = min(max(__float_as_uint(2.f * dt * __uint_as_float(m)) >> 23, 2u), 252u);
        cs = 2.f * dt * __uint_as_float((253u - e) << 23);
        if (lane == 0) sts32(dump + (2 * wg + half) * 3072, (e + 1u) << 23);
        an = kg_anchor_hi(kp, sel, dt, cs);
    } else {
        an = kg_anchor_lo(kp, sel, dt);
    }
    if (an.v[0] != 0xFFFFFFFFu) hook();
    float acc[24];
    const int nstep = wg == 2 ? 3 : 6;
#pragma unroll 1
    for (int c = 0; c < nstep; c++) {
        if (wg < 2) sel ^= 0x2200u;
        if (wg == 2 || (c & 1)) {
#pragma unroll
            for (int j = 0; j < 2; j++) { kp.l[j] = kp.l[j + 1]; kp.a[j] = kp.a[j + 1]; kp.r[j] = kp.r[j + 1]; kp.i[j] = kp.i[j + 1]; }
        }
        const uint32_t buf = scr + (2 * wg + (c & 1)) * 16384, tb = buf + lane * 128;
        if (!hi) {
            cpair p[4];
            p[0] = {an.v[0], an.v[1]}; p[1] = {an.v[2], an.v[3]};
            p[2] = pmul(p[0], an.v[4]); p[3] = pmul(p[1], an.v[4]);
#pragma unroll
            for (int j = 0; j < 4; j++) {
                cpair v[4];
#pragma unroll
                for (int i = 0; i < 4; i++) v[i] = j ? pmul(p[i], an.v[4 + j]) : p[i];
                const uint32_t a = tb + (((4 * half + j) ^ sw) << 4);
                sts128(a, make_uint4(v[0].r, v[1].r, v[2].r, v[3].r));
                sts128(a + 4096, make_uint4(v[0].i, v[1].i, v[2].i, v[3].i));
            }
            an = kg_anchor_lo(kp, sel, dt);
        } else {
            const uint32_t h1 = an.v[2], h2 = an.v[3], h256 = an.v[4], h512 = an.v[5], h1024 = an.v[6];
            cpair p[11];
            p[0] = {an.v[0], an.v[1]};
            p[1] = pmul(p[0], h2); p[2] = pmul(p[0], h1); p[3] = pmul(p[1], h1);
            p[4] = pmul(p[0], h256); p[5] = pmul(p[1], h256); p[6] = pmul(p[0], h512); p[7] = pmul(p[4], h512);
            p[8] = pmul({__byte_perm(p[0].r, p[4].r, 0x5410), __byte_perm(p[0].i, p[4].i, 0x5410)}, h1024);
            p[9] = pmul(p[8], h512); p[10] = pmul(p[8], h1024);
#pragma unroll
            for (int j = 0; j < 3; j++) {
                const uint32_t a = tb + 8192 + (((3 * half + j) ^ sw) << 4);
                sts128(a, make_uint4(p[4 * j].r, p[4 * j + 1].r, p[4 * j + 2].r, p[j < 2 ? 4 * j + 3 : 10].r));
                sts128(a + 4096, make_uint4(p[4 * j].i, p[4 * j + 1].i, p[4 * j + 2].i, p[j < 2 ? 4 * j + 3 : 10].i));
            }
            an = kg_anchor_hi(kp, sel, dt, cs);
        }
        if (c == 0) TS(24);
        if (c == 2) TS(26);
        fence_async_smem();
        wg_wait<0>();
        named_bar(5 + wg, 128);
        if (c == 1) TS(25);
        if (c == 2) TS(28);
        const uint64_t da = mkdesc(buf, 4096, 1024, 1);
        wg_fence();
#pragma unroll
        for (int k = 0; k < 4; k++) wgmma_kg(acc, da + k * 128, da + 512 + k * 128, k > 0 || c > 0);
        wg_commit();
    }
    const uint32_t ob = dump + (2 * wg + (hi ? 1 : 0)) * 3072, o = ob + ((16 * half + (lane >> 2)) * 24 + 2 * (lane & 3)) * 4;
    const float ci = __uint_as_float(lds32(ob));
    named_bar(5 + wg, 128);
    wg_wait<0>();
#pragma unroll
    for (int j = 0; j < 3; j++)
#pragma unroll
        for (int h = 0; h < 2; h++)
            asm volatile("st.shared.v2.f32 [%0], {%1, %2};" ::"r"(o + h * 768 + j * 32), "f"(fmaf(ci, hi ? acc[12 + 4 * j + 2 * h] : acc[4 * j + 2 * h], j + h ? 0.f : bf_lo(kp.ds))),
                         "f"(ci * (hi ? acc[13 + 4 * j + 2 * h] : acc[4 * j + 2 * h + 1])) : "memory");
}

__device__ __forceinline__ void kgen_expand(int d0, uint32_t dump, KgShared* ks, int ht TS_ARG) {
    const int lane = ht & 31;
    auto F = [](uint32_t x) { return __uint_as_float(x); };
#pragma unroll 1
    for (int c = 0; c < 5; c++) {
        float m = 0.f;
#pragma unroll
        for (int i = 0; i < 2; i++) {
            const uint32_t a = dump + c * 3072 + (ht + 96 * i) * 16;
            const uint4 x = lds128(a), y = c == 4 ? lds128(a + 3072) : make_uint4(0, 0, 0, 0);
            const float v0 = F(x.x) + F(y.x), v1 = F(x.y) + F(y.y), v2 = F(x.z) + F(y.z), v3 = F(x.w) + F(y.w);
            if (c == 4) sts128(a, make_uint4(__float_as_uint(v0), __float_as_uint(v1), __float_as_uint(v2), __float_as_uint(v3)));
            m = fmaxf(fmaxf(m, fmaxf(fabsf(v0), fabsf(v1))), fmaxf(fabsf(v2), fabsf(v3)));
        }
        const uint32_t mm = __reduce_max_sync(~0u, __float_as_uint(m));
        if (lane == 0) asm volatile("red.shared.max.u32 [%0], %1;" ::"r"(s2u(&ks->kmax[c])), "r"(mm) : "memory");
    }
    named_bar(4, 96);
    TSX(2, 6);
#pragma unroll 1
    for (int task = ht >> 5; task < 20; task += 3) {
        const int c = task >> 2, it = (task & 3) * 32 + lane, a = it >> 2, d = d0 + c;
        const uint4 o0 = lds128(dump + KG_IDX + it * 16), o1 = lds128(dump + KG_IDX + 2048 + it * 16);
        const uint32_t e = min(max(ks->kmax[c] >> 23, 4u), 250u), b = dump + c * 3072;
        const float sc = __uint_as_float((253u - e) << 23);
        if (it == 0) g_ksc[d] = e;
        uint32_t ev[4], ov[4];
#pragma unroll
        for (int i = 0; i < 4; i++) {
            const float x0 = F(lds32(b + (u4(o0, i) & 0xFFFF))), x1 = F(lds32(b + (u4(o0, i) >> 16)));
            const float y0 = F(lds32(b + (u4(o1, i) & 0xFFFF))), y1 = F(lds32(b + (u4(o1, i) >> 16)));
            ev[i] = pack2h((x0 + y0) * sc, (x1 + y1) * sc);
            ov[i] = pack2h((x0 - y0) * sc, (x1 - y1) * sc);
        }
        uint32_t* dst = &g_keo[d >> 1][a * 32 + (((4 * (d & 1) + (it & 3)) ^ (a & 7)) << 2)];
        stg128(dst, make_uint4(ev[0], ev[1], ev[2], ev[3]));
        stg128(dst + 1024, make_uint4(ov[0], ov[1], ov[2], ov[3]));
    }
}
#define Q_SCHED 0
#define Q_WAITFOR(it) (Q_SCHED == 0 ? (it) - 2 : Q_SCHED == 1 ? ((it) == 3 ? 1 : 0) : Q_SCHED == 2 ? -1 : (it) - 1)
#define Q_S0 6
#define Q_WGATE 0
#define Q_PREW 1
constexpr int Q_ST = 4;
constexpr int Q_AB = 16384, Q_BB = 30720, Q_SB = Q_AB + Q_BB;
constexpr int Q_EROW = 336;
constexpr int Q_ESLOT = 8 * Q_EROW;
constexpr int Q_EOFF = Q_ST * Q_SB;
constexpr int Q_KG = 2 * Q_SB;
constexpr int Q_KDUMP = Q_EOFF + 6 * Q_ESLOT;
static_assert(Q_KG + KG_TABLES <= Q_KDUMP, "kernel generation layout");
constexpr int Q_SMEM = Q_KDUMP + KG_DUMP + 1024;
__host__ __device__ constexpr int w_main(int j) { return (2 + (j >> 2)) * Q_SB + (j & 3) * 10240; }
__host__ __device__ constexpr int w_rem(int j) { return j < 4 ? (2 + (j >> 1)) * Q_SB + 40960 + (j & 1) * 2560 : 20480 + (j - 4) * 2560; }
constexpr int W_RES = 0, W_OUT = Q_SB;

__device__ unsigned g_epoch;
__device__ __align__(1024) unsigned long long g_stats[SEQ];
__device__ __align__(1024) uint4 g_csp[8][16][80];
__device__ __align__(1024) float g_colsum[3 * DM];
__device__ __align__(1024) uint4 g_halo[128][2][7][32];
__device__ __align__(1024) uint4 g_of[16][8][2][8][5][32];

__device__ __forceinline__ unsigned long long ld_ll(const unsigned long long* p) {
    unsigned long long v;
    asm volatile("ld.relaxed.gpu.global.b64 %0, [%1];" : "=l"(v) : "l"(p) : "memory");
    return v;
}
__device__ __forceinline__ void st_ll(unsigned long long* p, uint32_t payload, uint32_t tag) {
    const unsigned long long v = (unsigned long long)payload | ((unsigned long long)tag << 32);
    asm volatile("st.relaxed.gpu.global.b64 [%0], %1;" ::"l"(p), "l"(v) : "memory");
}
__device__ __forceinline__ uint4 ld_ll4(const uint4* p) {
    uint4 v;
    asm volatile("{\n.reg .b128 t;\n.reg .b64 a, b;\nld.relaxed.gpu.global.b128 t, [%4];\nmov.b128 {a, b}, t;\nmov.b64 {%0, %1}, a;\nmov.b64 {%2, %3}, b;\n}"
                 : "=r"(v.x), "=r"(v.y), "=r"(v.z), "=r"(v.w) : "l"(p) : "memory");
    return v;
}
__device__ __forceinline__ void st_ll4(uint4* p, uint32_t x, uint32_t y, uint32_t z, uint32_t w) {
    asm volatile("{\n.reg .b128 t;\n.reg .b64 a, b;\nmov.b64 a, {%1, %2};\nmov.b64 b, {%3, %4};\nmov.b128 t, {a, b};\nst.relaxed.gpu.global.b128 [%0], t;\n}"
                 ::"l"(p), "r"(x), "r"(y), "r"(z), "r"(w) : "memory");
}

__global__ void __launch_bounds__(384, 1)
attn_kernel(const __grid_constant__ CUtensorMap mX, const __grid_constant__ CUtensorMap mW, const __grid_constant__ CUtensorMap mWr,
            const __grid_constant__ CUtensorMap mWo, const __grid_constant__ CUtensorMap mWor, const __grid_constant__ CUtensorMap mRes,
            const __grid_constant__ CUtensorMap mOut, const bf16* xin, const bf16* __restrict__ wqkv, const bf16* __restrict__ wo,
            float* sums, const SsmParams sp, int layer, int slot) {
    extern __shared__ __align__(1024) char smraw[];
    __shared__ __align__(8) uint64_t s_full[Q_ST], s_empty[Q_ST], s_wfull[3], s_ex[8], s_res, s_idx, s_go, s_qdone, s_att, s_prep;
    __shared__ __align__(16) float s_cs[240], s_mean[2][72], s_rstd[2][72], s_red[4][32];
    __shared__ KgShared s_kg;
    const uint32_t sb = (s2u(smraw) + 1023) & ~1023u;
    const int tid = threadIdx.x, warp = __shfl_sync(~0u, tid >> 5, 0), lane = tid & 31;
    const int rank = blockIdx.x & 1, blk = blockIdx.x & 15, hg = blockIdx.x >> 4;
    const int g = lane >> 2, q = lane & 3;
    TS_DECL;
    TS_BEGIN;
    KgParams kp;
    const int srow = 1024 * (hg >> 2) + 64 * blk + 16 * (hg & 3);
    if (layer == 0) {
        kgen_load(kp, blockIdx.x * 5, warp, lane, sp);
#pragma unroll
        for (int i = 0; i < 7; i++)
            if (i < 6 || tid < 256) stg128(&g_of[blk][hg][0][0][0][0] + tid + 384 * i, make_uint4(0, 0, 0, 0));
        if (tid < 64) sums[(tid >> 4) * SEQ + srow + (tid & 15)] = 0.f;
    }
    if (tid < 5) s_kg.kmax[tid] = 0u;
    if (tid == 256) { prefetch_tmap(&mW); prefetch_tmap(&mWr); prefetch_tmap(&mX); }
    if (tid == 288) { prefetch_tmap(&mWo); prefetch_tmap(&mWor); prefetch_tmap(&mRes); prefetch_tmap(&mOut); }
    if (tid == 0) {
        for (int i = 0; i < Q_ST; i++) { mbar_init(s2u(&s_full[i]), 1); mbar_init(s2u(&s_empty[i]), 16); }
        for (int i = 0; i < 3; i++) mbar_init(s2u(&s_wfull[i]), 1);
        fence_mbar_init();
    }
    if (tid == 32) {
        for (int i = 0; i < 8; i++) mbar_init(s2u(&s_ex[i]), 1);
        mbar_init(s2u(&s_res), 1); mbar_init(s2u(&s_idx), 1); mbar_init(s2u(&s_go), 4); mbar_init(s2u(&s_qdone), 8); mbar_init(s2u(&s_att), 4); mbar_init(s2u(&s_prep), 96);
        fence_mbar_init();
    }
    __syncthreads();
    cluster_arrive_relaxed();
    cluster_wait();

    auto issue_w = [&](int it) {
        const int s = it & (Q_ST - 1);
        const uint32_t fb = s2u(&s_full[s]), db = sb + s * Q_SB + Q_AB + rank * 15360;
        const int k0 = it * 64 + rank * 32;
        mbar_expect(fb, Q_SB);
#pragma unroll
        for (int p = 0; p < 3; p++) tma2d_mc(db + p * 4096, &mW, p * DM + hg * 80, k0, fb, 3);
        tma3d_mc(db + 12288, &mWr, hg * 80 + 64, k0, 0, fb, 3);
    };
    auto issue_x = [&](int it) {
        const int s = it & (Q_ST - 1);
        tma3d(sb + s * Q_SB, &mX, (layer ? blk : it) * 64, (layer ? it : blk) * 64, 0, s2u(&s_full[s]));
    };
    if (layer == 0) {
        auto F = [](uint32_t x) { return __uint_as_float(x); };
        const int t2 = tid & 127, cl = min(lane, 29);
        const bf16* wsrc = wqkv + (size_t)(40 * blk + 10 * (warp & 3)) * (3 * DM) + (cl / 10) * DM + hg * 80 + 8 * (cl % 10);
        const bf16* xsrc = xin + (size_t)(2 * ((srow & 1023) + (t2 >> 3)) + (hg >> 2)) * DM + 8 * (t2 & 7);
        if (warp == 8) {
            if (elect_one()) {
#pragma unroll 1
                for (int it = 0; it < 2; it++) { issue_w(it); issue_x(it); }
                mbar_expect(s2u(&s_idx), 4096);
                bulk_g2s(sb + Q_KDUMP + KG_IDX, c_fft + 16 * 512, 4096, s2u(&s_idx));
            }
            __syncwarp();
        }
        kgen_tables(kp, sb + Q_KG, sb + Q_KDUMP, warp, lane, [&] {
            if (warp >= 8) {
                const char* wp = (const char*)(wqkv + (size_t)(40 * blk + min(t2, 119) / 3) * (3 * DM) + (t2 % 3) * DM + hg * 80);
                prefetch_l2(wp); prefetch_l2(wp + 128); prefetch_l2(wp + 159);
                prefetch_l2(xsrc + 56 * (t2 & 7));
                if ((t2 & 7) < 2) prefetch_l2(xsrc + 56 * (t2 & 7) + 512);
            } else {
                if (tid < 50) prefetch_l2((const char*)wo + (size_t)(blockIdx.x * 50 + tid) * 128);
                if (tid >= 64 && tid < 67 && blockIdx.x * 3 + tid - 64 < sizeof(c_fft) / 128) prefetch_l2((const char*)c_fft + (size_t)(blockIdx.x * 3 + tid - 64) * 128);
            }
        } TS_PASS);
        if (warp <= 8) asm volatile("bar.arrive 8, 384;" ::: "memory");
        fence_async_smem();
        cluster_arrive_relaxed();
        TS(1);
        if (warp >= 8) {
            uint4 v[10], u[10];
#pragma unroll
            for (int i = 0; i < 10; i++) v[i] = __ldg((const uint4*)(wsrc + (size_t)i * (3 * DM)));
#pragma unroll
            for (int i = 0; i < 10; i++) u[i] = __ldg((const uint4*)(xsrc + 64 * i));
            const uint32_t tag = 2u * ldg32(&g_epoch) + 1u;
            float cs[8] = {0.f, 0.f, 0.f, 0.f, 0.f, 0.f, 0.f, 0.f}, a = 0.f, b = 0.f;
#pragma unroll
            for (int i = 0; i < 10; i++)
#pragma unroll
                for (int j = 0; j < 4; j++) { cs[2 * j] += bf_lo(u4(v[i], j)); cs[2 * j + 1] += bf_hi(u4(v[i], j)); }
            const uint32_t pa = sb + Q_EOFF + 8192;
            if (lane < 30) {
                sts128(pa + ((warp & 3) * 240 + 8 * lane) * 4, make_uint4(__float_as_uint(cs[0]), __float_as_uint(cs[1]), __float_as_uint(cs[2]), __float_as_uint(cs[3])));
                sts128(pa + ((warp & 3) * 240 + 8 * lane + 4) * 4, make_uint4(__float_as_uint(cs[4]), __float_as_uint(cs[5]), __float_as_uint(cs[6]), __float_as_uint(cs[7])));
            }
#pragma unroll
            for (int i = 0; i < 10; i++)
#pragma unroll
                for (int j = 0; j < 4; j++) {
                    const float lo = bf_lo(u4(u[i], j)), hi = bf_hi(u4(u[i], j));
                    a += lo + hi; b = fmaf(lo, lo, fmaf(hi, hi, b));
                }
#pragma unroll
            for (int o = 1; o <= 4; o <<= 1) { a += __shfl_xor_sync(~0u, a, o); b += __shfl_xor_sync(~0u, b, o); }
            if ((t2 & 7) == 0) { s_red[0][t2 >> 3] = a; s_red[0][16 + (t2 >> 3)] = b; }
            named_bar(7, 128);
            if (t2 >= 48) {
                const int i = t2 - 48;
                float t[3];
#pragma unroll
                for (int j = 0; j < 3; j++)
                    t[j] = (F(lds32(pa + (3 * i + j) * 4)) + F(lds32(pa + (240 + 3 * i + j) * 4))) + (F(lds32(pa + (480 + 3 * i + j) * 4)) + F(lds32(pa + (720 + 3 * i + j) * 4)));
                st_ll4(&g_csp[hg][blk][i], __float_as_uint(t[0]), __float_as_uint(t[1]), __float_as_uint(t[2]), tag);
            }
            __syncwarp();
            TS(3);
        }
    }

    if (warp >= 8) {
        asm volatile("setmaxnreg.dec.sync.aligned.u32 88;");
        if (warp == 8) {
            if (layer == 0) cluster_wait();
            if (elect_one()) {
                if (layer) {
#pragma unroll 1
                    for (int it = 0; it < Q_PREW; it++) issue_w(it);
                    pdl_wait();
                }
#pragma unroll 1
                for (int it = layer ? 0 : 2; it < 10; it++) {
                    if (it >= Q_ST) mbar_wait(s2u(&s_empty[it & (Q_ST - 1)]), ((it >> 2) - 1) & 1);
                    else if (it > 0 && Q_WAITFOR(it) >= 0) mbar_wait(s2u(&s_full[Q_WAITFOR(it)]), 0);
                    issue_x(it);
                    if (it >= Q_PREW || layer == 0) issue_w(it);
                }
#pragma unroll 1
                for (int b = 0; b < 3; b++) {
                    const uint32_t fb = s2u(&s_wfull[b]);
                    mbar_wait(s2u(&s_empty[(2 + b) & 3]), b < 2);
                    TS(11 + b);
                    if (b == 2) {
                        mbar_expect(s2u(&s_res), 20480);
                        if (layer == 0) tma3d(sb + W_RES, &mX, hg * 80, blk * 64, 0, s2u(&s_res));
                        tma3d(sb + W_RES + (layer ? 0 : 16384), &mRes, layer ? blk * 64 : hg * 80 + 64, layer ? hg * 80 : blk * 64, 0, s2u(&s_res));
                    }
                    mbar_expect(fb, b < 2 ? 46080 : 10240);
#pragma unroll 1
                    for (int i = 0; i < 4; i++) {
                        if (b < 2) tma2d_mc(sb + w_main(4 * b) + i * 10240 + rank * 5120, &mWo, hg * 80, ((hg + 4 * b + i) & 7) * 80 + rank * 40, fb, 3);
                        if (b == 2 || i < 2) tma2d_mc(sb + w_rem(2 * b) + i * 2560 + rank * 1280, &mWor, hg * 80 + 64, ((hg + 2 * b + i) & 7) * 80 + rank * 40, fb, 3);
                    }
                }
            }
            __syncwarp();
        } else {
            const int ht = tid - 288, hw = warp - 9;
            auto F = [](uint32_t x) { return __uint_as_float(x); };
            const uint32_t tag = 2u * ldg32(&g_epoch) + layer + 1u;
            if (layer == 0) {
                if (ht < 16) {
                    asm volatile("fence.release.gpu;" ::: "memory");
                    st_ll(g_stats + srow + ht, ln_finish_packed(s_red[0][ht], s_red[0][16 + ht]), tag);
                }
            } else {
                pdl_wait();
                pdl_launch();
                if (ht == 0) TSX(2, 2);
                const bf16* src = xin + (size_t)(ht >> 1) * XP + srow + 8 * (lane & 1);
                uint4 v[14];
#pragma unroll
                for (int i = 0; i < 14; i++) {
                    v[i] = make_uint4(0, 0, 0, 0);
                    if (i < 13 || hw == 0) v[i] = ldg128(src + (size_t)48 * i * XP);
                }
                float a[16];
#pragma unroll
                for (int j = 0; j < 16; j++) a[j] = 0.f;
#pragma unroll
                for (int i = 0; i < 14; i++)
#pragma unroll
                    for (int j = 0; j < 4; j++) {
                        const float lo = bf_lo(u4(v[i], j)), hi = bf_hi(u4(v[i], j));
                        a[2 * j] += lo; a[8 + 2 * j] = fmaf(lo, lo, a[8 + 2 * j]); a[2 * j + 1] += hi; a[9 + 2 * j] = fmaf(hi, hi, a[9 + 2 * j]);
                    }
                if (ht == 0) TSX(2, 8);
#pragma unroll
                for (int l = 0; l < 4; l++) {
                    const int n = 8 >> l;
                    const bool up = lane & (2 * n);
#pragma unroll
                    for (int j = 0; j < 8; j++)
                        if (j < n) { const float lo = a[j], hi = a[j + n]; a[j] = (up ? hi : lo) + __shfl_xor_sync(~0u, up ? lo : hi, 2 * n); }
                }
                s_red[hw][(lane & 16) + 8 * (lane & 1) + ((lane >> 1) & 7)] = a[0];
                named_bar(4, 96);
                if (ht < 16) st_ll(g_stats + srow + ht, ln_finish_packed(s_red[0][ht] + s_red[1][ht] + s_red[2][ht], s_red[0][16 + ht] + s_red[1][16 + ht] + s_red[2][16 + ht]), tag);
            }
            if (ht == 0) TSX(2, 4);
            if (ht < 80) {
                float t[3] = {0.f, 0.f, 0.f};
                int ci[3];
#pragma unroll
                for (int j = 0; j < 3; j++) ci[j] = ((3 * ht + j) / 80) * DM + hg * 80 + (3 * ht + j) % 80;
                if (layer == 0) {
                    uint4 v[16];
                    int spin = 0;
                    bool ok;
                    do {
                        ok = true;
#pragma unroll
                        for (int j = 0; j < 16; j++) v[j] = ld_ll4(&g_csp[hg][j][ht]);
#pragma unroll
                        for (int j = 0; j < 16; j++) ok = ok && v[j].w == tag;
                    } while (!ok && ++spin < (1 << 18));
#pragma unroll
                    for (int j = 0; j < 16; j++) { t[0] += F(v[j].x); t[1] += F(v[j].y); t[2] += F(v[j].z); }
                    if (blk == 0) { g_colsum[ci[0]] = t[0]; g_colsum[ci[1]] = t[1]; g_colsum[ci[2]] = t[2]; }
                } else {
#pragma unroll
                    for (int j = 0; j < 3; j++) t[j] = F(ldg32(g_colsum + ci[j]));
                }
#pragma unroll
                for (int j = 0; j < 3; j++) s_cs[3 * ht + j] = t[j];
            }
            if (ht == 0) TSX(2, 15);
            if (ht < 72) {
                const unsigned long long* sp0 = g_stats + 64 * blk + ((blk || ht >= 8) ? ht - 8 : 0);
                unsigned long long v0, v1;
                int spin = 0;
                do { v0 = ld_ll(sp0); v1 = ld_ll(sp0 + 1024); } while (((uint32_t)(v0 >> 32) != tag || (uint32_t)(v1 >> 32) != tag) && ++spin < (1 << 18));
                s_mean[0][ht] = bf_hi((uint32_t)v0); s_rstd[0][ht] = frcp(bf_lo((uint32_t)v0));
                s_mean[1][ht] = bf_hi((uint32_t)v1); s_rstd[1][ht] = frcp(bf_lo((uint32_t)v1));
            }
            asm volatile("fence.acquire.gpu;" ::: "memory");
            mbar_arrive(s2u(&s_prep));
            if (ht == 0) TSX(2, 5);
            if (layer == 0) {
                __syncwarp();
                cluster_wait();
                named_bar(8, 384);
                mbar_wait(s2u(&s_idx), 0);
                kgen_expand(blockIdx.x * 5, sb + Q_KDUMP, &s_kg, ht TS_PASS);
                asm volatile("fence.release.gpu;" ::: "memory");
                named_bar(4, 96);
                pdl_launch();
                if (ht == 0) TSX(2, 7);
            }
        }
        TS_END(slot);
    } else {
    asm volatile("setmaxnreg.inc.sync.aligned.u32 208;");
    const int wg = warp >> 2, w = warp & 3;
    const int mi = lane >> 3, mj = lane & 7;
    TS(2);
    float acc[120];
    auto release = [&](int it) {
        if (lane == 0) { mbar_arrive_cta(s2u(&s_empty[it & (Q_ST - 1)]), 0); mbar_arrive_cta(s2u(&s_empty[it & (Q_ST - 1)]), 1); }
    };
#pragma unroll 1
    for (int it = 0; it < 10; it++) {
        const int s = it & (Q_ST - 1);
        const uint32_t st = sb + s * Q_SB;
        const bool hold = wg == 1 && it == Q_S0;
        if (hold) {
            wg_wait<0>();
            release(it - 1);
            mbar_wait(s2u(&s_go), 0);
        }
        mbar_wait(s2u(&s_full[s]), (it >> 2) & 1);
        if (it < 2) TS(3 + it);
        if (it == 6) TS(5);
        if (it == 9) TS(6);
        const uint64_t da = mkdesc(st + wg * 8192, 16, 1024, 1);
        const uint64_t db = mkdesc(st + Q_AB, 4096, 1024, 1);
        const uint64_t dr = mkdesc(st + Q_AB + 12288, 1024, 256, 3);
        wg_fence();
        if (layer == 0) {
#pragma unroll
            for (int ks = 0; ks < 4; ks++) {
                const int sc = (ks > 0) ? 1 : (it > 0);
                wgmma_n192<0, 1>(*(float(*)[96]) & acc[0], da + ks * 2, db + (ks >> 1) * 960 + (ks & 1) * 128, sc);
                wgmma_n48<0, 1>(*(float(*)[24]) & acc[96], da + ks * 2, dr + (ks >> 1) * 960 + (ks & 1) * 32, sc);
            }
            wg_commit();
        } else {
#pragma unroll
            for (int ks = 0; ks < 4; ks++) {
                const int sc = (ks > 0) ? 1 : (it > 0);
                wgmma_n192<1, 1>(*(float(*)[96]) & acc[0], da + ks * 128, db + (ks >> 1) * 960 + (ks & 1) * 128, sc);
                wgmma_n48<1, 1>(*(float(*)[24]) & acc[96], da + ks * 128, dr + (ks >> 1) * 960 + (ks & 1) * 32, sc);
            }
            wg_commit();
        }
        wg_wait<1>();
        if (it > 0 && !hold) release(it - 1);
    }
    if (wg == 0 && lane == 0) mbar_arrive(s2u(&s_go));
    const uint32_t tag = 2u * ldg32(&g_epoch) + layer + 1u;
    if (layer == 0) cluster_wait();
    mbar_wait(s2u(&s_prep), 0);
    const bool first = (blk == 0 && w == 0);
    const bool sel0 = (2 * q > g), sel1 = (2 * q + 1 > g);
    constexpr float SC = 0.22360679774997896f * 1.4426950408889634f;
    const float m0 = s_mean[wg][8 + 16 * w + g], m1 = s_mean[wg][16 + 16 * w + g];
    const float* rs = &s_rstd[wg][16 * w];
    const float kx0 = rs[2 * q + (sel0 ? 0 : 8)], kx1 = rs[2 * q + (sel1 ? 1 : 9)], ky0 = rs[2 * q + (sel0 ? 8 : 16)], ky1 = rs[2 * q + (sel1 ? 9 : 17)];
    const float cx0 = SC * rs[8 + g] * kx0, cx1 = SC * rs[8 + g] * kx1, cy0 = SC * rs[16 + g] * ky0, cy1 = SC * rs[16 + g] * ky1;
    wg_wait<0>();
    TS(7);
    if (lane == 0) mbar_arrive(s2u(&s_qdone));
    uint32_t ql[10], qh[10], kl[10], kh[10], vl[10], vh[10];
    auto fold = [&](int p, int f, uint32_t& lo, uint32_t& hi) {
        const int j = (f < 8) ? 8 * p + f : 24 + 2 * p + (f - 8);
        const float2 c = *(const float2*)&s_cs[p * 80 + 8 * f + 2 * q];
        lo = pack2(fmaf(-m0, c.x, acc[4 * j]), fmaf(-m0, c.y, acc[4 * j + 1]));
        hi = pack2(fmaf(-m1, c.x, acc[4 * j + 2]), fmaf(-m1, c.y, acc[4 * j + 3]));
    };
#pragma unroll
    for (int f = 0; f < 10; f++) { fold(1, f, kl[f], kh[f]); fold(2, f, vl[f], vh[f]); }
    if (w == 3) {
        uint4* hp = &g_halo[blockIdx.x][wg][0][lane];
        st_ll4(hp, kh[0], kh[1], kh[2], tag); st_ll4(hp + 32, kh[3], kh[4], kh[5], tag); st_ll4(hp + 64, kh[6], kh[7], kh[8], tag);
        st_ll4(hp + 96, kh[9], vh[0], vh[1], tag); st_ll4(hp + 128, vh[2], vh[3], vh[4], tag); st_ll4(hp + 160, vh[5], vh[6], vh[7], tag);
        st_ll4(hp + 192, vh[8], vh[9], 0u, tag);
    } else {
        const uint32_t a = sb + Q_EOFF + (warp - wg) * Q_ESLOT + mj * Q_EROW + mi * 16;
        stsm_x4(a, kh[0], kh[1], kh[2], kh[3]);
        stsm_x4(a + 64, kh[4], kh[5], kh[6], kh[7]);
        stsm_x4(a + 128, kh[8], kh[9], vh[0], vh[1]);
        stsm_x4(a + 192, vh[2], vh[3], vh[4], vh[5]);
        stsm_x4(a + 256, vh[6], vh[7], vh[8], vh[9]);
        __syncwarp();
        if (lane == 0) mbar_arrive(s2u(&s_ex[warp]));
    }
    TS(9);
#pragma unroll
    for (int f = 0; f < 10; f++) fold(0, f, ql[f], qh[f]);
    uint32_t vt1[10], vt2[10];
#pragma unroll
    for (int f = 0; f < 10; f++) { vt1[f] = movm_t(vl[f]); vt2[f] = movm_t(vh[f]); }
    TS(10);
    uint32_t kp[10], vp[10];
    if (w > 0) {
        const uint32_t a = sb + Q_EOFF + (warp - wg - 1) * Q_ESLOT + mj * Q_EROW + mi * 16;
        mbar_wait(s2u(&s_ex[warp - 1]), 0);
        ldsm_x4(kp[0], kp[1], kp[2], kp[3], a);
        ldsm_x4(kp[4], kp[5], kp[6], kp[7], a + 64);
        ldsm_x2(kp[8], kp[9], a + 128);
        ldsm_x4_t(vp[0], vp[1], vp[2], vp[3], a + 160);
        ldsm_x4_t(vp[4], vp[5], vp[6], vp[7], a + 224);
        ldsm_x2_t(vp[8], vp[9], a + 288 - (lane >> 4) * 32);
    } else if (blk > 0) {
        const uint4* hp = &g_halo[blockIdx.x - 1][wg][0][lane];
        uint4 hv[7];
        int spin = 0;
        bool ok;
        do {
            ok = true;
#pragma unroll
            for (int f = 0; f < 7; f++) hv[f] = ld_ll4(hp + 32 * f);
#pragma unroll
            for (int f = 0; f < 7; f++) ok = ok && hv[f].w == tag;
        } while (!__all_sync(~0u, ok) && ++spin < (1 << 18));
#pragma unroll
        for (int f = 0; f < 10; f++) { kp[f] = u4(hv[f / 3], f % 3); vp[f] = movm_t(u4(hv[(10 + f) / 3], (10 + f) % 3)); }
    } else {
#pragma unroll
        for (int f = 0; f < 10; f++) { kp[f] = 0u; vp[f] = 0u; }
    }
    TS(12);
    float oacc[10][4];
#pragma unroll
    for (int h = 0; h < 4; h++) {
        const int fa = (h == 0) ? 0 : (h == 1) ? 3 : (h == 2) ? 5 : 8, fb = fa + 1, fh = (h < 2) ? 2 : 7;
        const bool mine = (h & 1) ? (q >= 2) : (q < 2);
        const uint32_t qml = mine ? ql[fh] : 0u, qmh = mine ? qh[fh] : 0u;
        float S0[4] = {0.f, 0.f, 0.f, 0.f}, S1[4] = {0.f, 0.f, 0.f, 0.f}, S2[4] = {0.f, 0.f, 0.f, 0.f};
        mma16816(S0, ql[fa], qh[fa], ql[fb], qh[fb], kp[fa], kp[fb]); mma1688(S0, qml, qmh, kp[fh]);
        mma16816(S1, ql[fa], qh[fa], ql[fb], qh[fb], kl[fa], kl[fb]); mma1688(S1, qml, qmh, kl[fh]);
        mma16816(S2, ql[fa], qh[fa], ql[fb], qh[fb], kh[fa], kh[fb]); mma1688(S2, qml, qmh, kh[fh]);
        float x0 = (sel0 ? S0[0] : S1[0]) * cx0, x1 = (sel1 ? S0[1] : S1[1]) * cx1;
        float y0 = (sel0 ? S1[2] : S2[2]) * cy0, y1 = (sel1 ? S1[3] : S2[3]) * cy1;
        if (first) { if (sel0) x0 = -INFINITY; if (sel1) x1 = -INFINITY; }
        float mx = fmaxf(x0, x1), my = fmaxf(y0, y1);
        mx = fmaxf(mx, __shfl_xor_sync(~0u, mx, 1)); my = fmaxf(my, __shfl_xor_sync(~0u, my, 1));
        mx = fmaxf(mx, __shfl_xor_sync(~0u, mx, 2)); my = fmaxf(my, __shfl_xor_sync(~0u, my, 2));
        x0 = ex2(x0 - mx); x1 = ex2(x1 - mx); y0 = ex2(y0 - my); y1 = ex2(y1 - my);
        float sx = x0 + x1, sy = y0 + y1;
        sx += __shfl_xor_sync(~0u, sx, 1); sy += __shfl_xor_sync(~0u, sy, 1);
        sx += __shfl_xor_sync(~0u, sx, 2); sy += __shfl_xor_sync(~0u, sy, 2);
        const float ix = frcp(sx), iy = frcp(sy);
        x0 *= ix * kx0; x1 *= ix * kx1; y0 *= iy * ky0; y1 *= iy * ky1;
        const uint32_t pa0 = pack2(sel0 ? x0 : 0.f, sel1 ? x1 : 0.f);
        const uint32_t pa2 = pack2(sel0 ? 0.f : x0, sel1 ? 0.f : x1);
        const uint32_t pa3 = pack2(sel0 ? y0 : 0.f, sel1 ? y1 : 0.f);
        const uint32_t pb1 = pack2(sel0 ? 0.f : y0, sel1 ? 0.f : y1);
#pragma unroll
        for (int i = 0; i < 3; i++) {
            const int f = (i == 0) ? fa : (i == 1) ? fb : fh;
            float O[4] = {0.f, 0.f, 0.f, 0.f};
            mma16816(O, pa0, 0u, pa2, pa3, vp[f], vt1[f]);
            mma1688(O, 0u, pb1, vt2[f]);
            if (i < 2 || !(h & 1) || mine) { oacc[f][0] = O[0]; oacc[f][1] = O[1]; oacc[f][2] = O[2]; oacc[f][3] = O[3]; }
        }
    }
    TS(13);
    uint4 of[5][5];
    {
        uint4* dst = &g_of[blk][hg][layer][warp][0][lane];
#pragma unroll
        for (int k = 0; k < 5; k++) {
            of[0][k] = make_uint4(pack2(oacc[2 * k][0], oacc[2 * k][1]), pack2(oacc[2 * k][2], oacc[2 * k][3]),
                                  pack2(oacc[2 * k + 1][0], oacc[2 * k + 1][1]), pack2(oacc[2 * k + 1][2], oacc[2 * k + 1][3]));
            st_ll4(dst + 32 * k, of[0][k].x ? of[0][k].x : 0x80000000u, of[0][k].y, of[0][k].z, of[0][k].w);
        }
    }
    if (Q_WGATE && wg == 1 && lane == 0) mbar_arrive(s2u(&s_att));
    TS(14);
    const uint4* osrc = &g_of[blk][0][layer][warp][0][lane];
    auto oload = [&](int j) {
        const uint4* p = osrc + ((hg + j) & 7) * 2560;
#pragma unroll
        for (int k = 0; k < 5; k++) of[j % 5][k] = ld_ll4(p + 32 * k);
    };
    {
        const uint32_t* pp = &g_of[blk][(hg + 1 + (lane & 3)) & 7][layer][warp][4][31].x;
        uint32_t v;
        int spin = 0;
        do { asm volatile("ld.relaxed.gpu.global.u32 %0, [%1];" : "=r"(v) : "l"(pp) : "memory"); } while (!__all_sync(~0u, v != 0u) && ++spin < (1 << 18));
    }
    TS(15);
#pragma unroll
    for (int j = 1; j < 5; j++) oload(j);
    float a64[32], a16[8];
    if (Q_WGATE && wg == 0) mbar_wait(s2u(&s_att), 0);
#pragma unroll
    for (int j = 0; j < 8; j++) {
        if (j == 0 || j == 2 || j == 4) mbar_wait(s2u(&s_wfull[j >> 1]), 0);
        if (j > 0) {
            int spin = 0;
            while (true) {
                bool ok = true;
#pragma unroll
                for (int k = 0; k < 5; k++) ok = ok && of[j % 5][k].x != 0u;
                if (__all_sync(~0u, ok) || ++spin >= (1 << 18)) break;
                oload(j);
            }
        }
        if (j == 0) TS(16);
        if (j == 1) TS(17);
        if (j == 5) TS(18);
        const uint64_t dm = mkdesc(sb + w_main(j), 4096, 1024, 1), dr = mkdesc(sb + w_rem(j), 1024, 256, 3);
        wg_fence();
#pragma unroll
        for (int k = 0; k < 5; k++) {
            wgmma_rs64(a64, of[j % 5][k], dm + k * 128, j + k > 0);
            wgmma_rs16(a16, of[j % 5][k], dr + k * 32, j + k > 0);
        }
        wg_commit();
        if (j >= 1 && j <= 3) { wg_wait<1>(); oload(j + 4); }
    }
    uint32_t res[20];
    mbar_wait(s2u(&s_res), 0);
    const uint32_t ta = (8 * (mi >> 1) + mj) * 128 + (((2 * w + (mi & 1)) ^ mj) << 4);
    if (layer == 0) {
        const int tok = 16 * w + 8 * (mi & 1) + mj;
#pragma unroll
        for (int k = 0; k < 4; k++)
            ldsm_x4(res[4 * k], res[4 * k + 1], res[4 * k + 2], res[4 * k + 3], sb + W_RES + wg * 8192 + tok * 128 + (((2 * k + (mi >> 1)) ^ mj) << 4));
        ldsm_x4(res[16], res[17], res[18], res[19], sb + W_RES + 16384 + wg * 2048 + tok * 32 + (((mi >> 1) ^ (mj >> 2)) << 4));
    } else {
#pragma unroll
        for (int k = 0; k < 5; k++) ldsm_x4_t(res[4 * k], res[4 * k + 1], res[4 * k + 2], res[4 * k + 3], sb + W_RES + wg * 10240 + k * 2048 + ta);
    }
    mbar_wait(s2u(&s_qdone), 0);
    wg_wait<0>();
    TS(19);
#pragma unroll
    for (int i = 0; i < 20; i++) {
        const uint32_t y = i < 16 ? pack2(a64[2 * i], a64[2 * i + 1]) : pack2(a16[2 * i - 32], a16[2 * i - 31]);
        asm("add.rn.bf16x2 %0, %0, %1;" : "+r"(res[i]) : "r"(y));
    }
#pragma unroll
    for (int k = 0; k < 5; k++) stsm_x4_t(sb + W_OUT + wg * 10240 + k * 2048 + ta, res[4 * k], res[4 * k + 1], res[4 * k + 2], res[4 * k + 3]);
    fence_async_smem();
    named_bar(1 + wg, 128);
    if ((tid & 127) == 0) {
        asm volatile("cp.async.bulk.tensor.2d.global.shared::cta.bulk_group [%0, {%2, %3}], [%1];"
                     ::"l"(&mOut), "r"(sb + W_OUT + wg * 10240), "r"(1024 * wg + 64 * blk), "r"(hg * 80) : "memory");
        asm volatile("cp.async.bulk.commit_group;" ::: "memory");
    }
    TS(20);
    {
        float sm[4] = {0.f, 0.f, 0.f, 0.f}, d0[4] = {0.f, 0.f, 0.f, 0.f}, d1[4] = {0.f, 0.f, 0.f, 0.f};
#pragma unroll
        for (int k = 0; k < 5; k++) {
            mma16816(sm, res[4 * k], res[4 * k + 1], res[4 * k + 2], res[4 * k + 3], 0x3F803F80u, 0x3F803F80u);
            mma16816(d0, res[4 * k], res[4 * k + 1], res[4 * k + 2], res[4 * k + 3], res[4 * k], res[4 * k + 2]);
            mma16816(d1, res[4 * k], res[4 * k + 1], res[4 * k + 2], res[4 * k + 3], res[4 * k + 1], res[4 * k + 3]);
        }
        const bool diag = q == (g >> 1);
        if (diag || q == ((g >> 1) ^ 1)) {
            float* dst = sums + (2 * layer + diag) * SEQ + 1024 * wg + 64 * blk + 16 * w + g;
            asm volatile("red.global.add.f32 [%0], %1;" ::"l"(dst), "f"(diag ? ((g & 1) ? d0[1] : d0[0]) : sm[0]) : "memory");
            asm volatile("red.global.add.f32 [%0], %1;" ::"l"(dst + 8), "f"(diag ? ((g & 1) ? d1[3] : d1[2]) : sm[2]) : "memory");
        }
    }
    TS(21);
    if ((tid & 127) == 0) asm volatile("cp.async.bulk.wait_group 0;" ::: "memory");
    TS_END(slot);
    }
}
__device__ __forceinline__ void wgmma_h64_rs(uint32_t (&d)[16], const uint4& a, uint64_t db, int scale_d) {
    asm volatile("{\n.reg .pred p;\nsetp.ne.b32 p, %21, 0;\n"
                 "wgmma.mma_async.sync.aligned.m64n64k16.f16.f16.f16 {%0,%1,%2,%3,%4,%5,%6,%7,%8,%9,%10,%11,%12,%13,%14,%15}, {%16,%17,%18,%19}, %20, p, 1, 1, 1;\n}\n"
                 : "+r"(d[0]), "+r"(d[1]), "+r"(d[2]), "+r"(d[3]), "+r"(d[4]), "+r"(d[5]), "+r"(d[6]), "+r"(d[7]), "+r"(d[8]), "+r"(d[9]),
                   "+r"(d[10]), "+r"(d[11]), "+r"(d[12]), "+r"(d[13]), "+r"(d[14]), "+r"(d[15])
                 : "r"(a.x), "r"(a.y), "r"(a.z), "r"(a.w), "l"(db), "r"(scale_d));
}
__device__ __forceinline__ void wgmma_h32_rs(uint32_t (&d)[8], const uint32_t (&a)[4], uint64_t db, int scale_d) {
    asm volatile("{\n.reg .pred p;\nsetp.ne.b32 p, %13, 0;\n"
                 "wgmma.mma_async.sync.aligned.m64n32k16.f16.f16.f16 {%0,%1,%2,%3,%4,%5,%6,%7}, {%8,%9,%10,%11}, %12, p, 1, 1, 0;\n}\n"
                 : "+r"(d[0]), "+r"(d[1]), "+r"(d[2]), "+r"(d[3]), "+r"(d[4]), "+r"(d[5]), "+r"(d[6]), "+r"(d[7])
                 : "r"(a[0]), "r"(a[1]), "r"(a[2]), "r"(a[3]), "l"(db), "r"(scale_d));
}
__device__ __forceinline__ void wgmma_sp64_rs(float (&d)[32], const uint4& a, uint64_t db, uint32_t meta, int scale_d) {
    asm volatile("{\n.reg .pred p;\nsetp.ne.b32 p, %38, 0;\n"
                 "wgmma.mma_async.sp.sync.aligned.m64n64k32.f32.f16.f16 "
                 "{%0,%1,%2,%3,%4,%5,%6,%7,%8,%9,%10,%11,%12,%13,%14,%15,%16,%17,%18,%19,%20,%21,%22,%23,%24,%25,%26,%27,%28,%29,%30,%31}, "
                 "{%32,%33,%34,%35}, %36, %37, 0, p, 1, 1, 1;\n}\n"
                 : "+f"(d[0]), "+f"(d[1]), "+f"(d[2]), "+f"(d[3]), "+f"(d[4]), "+f"(d[5]), "+f"(d[6]), "+f"(d[7]), "+f"(d[8]), "+f"(d[9]),
                   "+f"(d[10]), "+f"(d[11]), "+f"(d[12]), "+f"(d[13]), "+f"(d[14]), "+f"(d[15]), "+f"(d[16]), "+f"(d[17]), "+f"(d[18]), "+f"(d[19]),
                   "+f"(d[20]), "+f"(d[21]), "+f"(d[22]), "+f"(d[23]), "+f"(d[24]), "+f"(d[25]), "+f"(d[26]), "+f"(d[27]), "+f"(d[28]), "+f"(d[29]),
                   "+f"(d[30]), "+f"(d[31])
                 : "r"(a.x), "r"(a.y), "r"(a.z), "r"(a.w), "l"(db), "r"(meta), "r"(scale_d));
}

#define F_KFIRST 1
constexpr int F_S23 = 0;
constexpr int F_WG = 8192, F_WGB = 24576;
constexpr int F_SMEM = F_WG + 3 * F_WGB + 1024;

__device__ __forceinline__ void fft_stage(const uint32_t (&u)[2][2][4], uint32_t eo, int warp4, int lane) {
    const int mi = lane >> 3, mj = lane & 7;
#pragma unroll
    for (int c = 0; c < 2; c++) {
        const uint32_t a = eo + (8 * warp4 + mj) * 128 + (((4 * c + mi) ^ mj) << 4);
        stsm_x4(a, hadd(u[c][0][0], u[c][1][0]), hadd(u[c][0][1], u[c][1][1]), hadd(u[c][0][2], u[c][1][2]), hadd(u[c][0][3], u[c][1][3]));
        stsm_x4(a + 4096, hsub(u[c][0][0], u[c][1][0]), hsub(u[c][0][1], u[c][1][1]), hsub(u[c][0][2], u[c][1][2]), hsub(u[c][0][3], u[c][1][3]));
    }
    fence_async_smem();
}
__device__ __forceinline__ void fft_forward(const uint4 (&a1)[4], const uint4 (&tw)[4], uint32_t eo, uint32_t s2, uint32_t (&X)[2][2][8]) {
    uint32_t dr[16], di[16];
    const uint64_t de = mkdesc(eo, 4096, 1024, 1), d2 = mkdesc(s2, 16, 1024, 1);
    wg_fence();
    wgmma_h64_rs(dr, a1[0], de, 0);
    wgmma_h64_rs(di, a1[2], de + 256, 0);
    wgmma_h64_rs(dr, a1[1], de + 128, 1);
    wgmma_h64_rs(di, a1[3], de + 384, 1);
    wg_commit();
    wg_wait<0>();
#pragma unroll
    for (int c = 0; c < 2; c++) {
        uint32_t zr[2][4], zi[2][4];
#pragma unroll
        for (int p = 0; p < 2; p++)
#pragma unroll
            for (int i = 0; i < 4; i++) {
                const uint32_t r = dr[8 * c + 4 * p + i], m = di[8 * c + 4 * p + i], tr = u4(tw[p], i), ti = u4(tw[2 + p], i);
                zr[p][i] = hfms(m, ti, hmul(r, tr));
                zi[p][i] = hfma(m, tr, hmul(r, ti));
            }
        wg_fence();
        wgmma_h32_rs(X[c][0], zr[0], d2, 0);
        wgmma_h32_rs(X[c][1], zr[1], d2 + 4, 0);
        wgmma_h32_rs(X[c][0], zi[0], d2 + 2, 1);
        wgmma_h32_rs(X[c][1], zi[1], d2 + 6, 1);
        wg_commit();
    }
}

__global__ void __launch_bounds__(384, 1) conv_kernel(const bf16* xT, const float* sums, bf16* out, int slot) {
    extern __shared__ __align__(1024) char smraw[];
    __shared__ __align__(8) uint64_t kbar;
    const uint32_t sb = (s2u(smraw) + 1023) & ~1023u;
    const int tid = threadIdx.x, warp = __shfl_sync(~0u, tid >> 5, 0), lane = tid & 31;
    const int wg = warp >> 2, w = warp & 3, t = tid & 127, g = lane >> 2, q = lane & 3, mi = lane >> 3, mj = lane & 7;
    const int npair = min(3, DM / 2 - 3 * (int)blockIdx.x), ch0 = 6 * blockIdx.x + 2 * wg;
    const uint32_t wb = sb + F_WG + wg * F_WGB;
    TS_DECL;
    TS_BEGIN;
    if (tid == 0) {
        mbar_init(s2u(&kbar), 1);
        fence_mbar_init();
        mbar_expect(s2u(&kbar), 8192 + npair * 8192);
#pragma unroll 1
        for (int i = 0; i < npair; i++) bulk_g2s(sb + F_WG + i * F_WGB + 8192, g_keo[3 * blockIdx.x + i], 8192, s2u(&kbar));
        bulk_g2s(sb + F_S23, c_fft + 18 * 512, 8192, s2u(&kbar));
    }
    uint4 a1[4], tw[4];
#pragma unroll
    for (int i = 0; i < 4; i++) { a1[i] = ldg_tab(i, t); tw[i] = ldg_tab(8 + i, t); }
    __syncthreads();
    pdl_launch();
    if (wg >= npair) return;
    uint32_t u[2][2][4], KH[2][2][8];
    const uint2 ke = ldg64(g_ksc + ch0);
    const uint32_t oscale[2] = {(ke.x + 3u) * 0x00800080u, (ke.y + 3u) * 0x00800080u};
    TS(1);
    mbar_wait(s2u(&kbar), 0);
    TS(2);
    fft_forward(a1, tw, wb + 8192, sb + F_S23, KH);
#pragma unroll
    for (int i = 0; i < 4; i++) tw[i] = ldg_tab(4 + i, t);
    TS(4);
    pdl_wait();
    TS(5);
    uint2 x[2][2][2];
    const int ra[2] = {16 * (8 * w + g) + 4 * q, 16 * (63 - 8 * w - g) + 4 * q};
    {
        uint4 s[2][2][2];
#pragma unroll
        for (int h = 0; h < 2; h++)
#pragma unroll
            for (int p = 0; p < 2; p++) {
                s[h][p][0] = ldg128(sums + 1024 * p + ra[h]);
                s[h][p][1] = ldg128(sums + SEQ + 1024 * p + ra[h]);
#pragma unroll
                for (int c = 0; c < 2; c++) x[c][h][p] = ldg64(xT + (size_t)(ch0 + c) * XP + 1024 * p + ra[h]);
            }
        TS(6);
        TS(7);
#pragma unroll
        for (int h = 0; h < 2; h++)
#pragma unroll
            for (int j = 0; j < 4; j++) {
                const uint4 sa = s[h][j >> 1][0], sq = s[h][j >> 1][1];
                const float4 v = make_float4(__uint_as_float(u4(sa, 2 * (j & 1))), __uint_as_float(u4(sq, 2 * (j & 1))),
                                             __uint_as_float(u4(sa, 2 * (j & 1) + 1)), __uint_as_float(u4(sq, 2 * (j & 1) + 1)));
                const float m0 = v.x * (1.0f / DM), m1 = v.z * (1.0f / DM);
                const float r0 = frsq(fmaxf(fmaf(v.y, 1.0f / DM, fmaf(-m0, m0, 1e-5f)), 1e-5f));
                const float r1 = frsq(fmaxf(fmaf(v.w, 1.0f / DM, fmaf(-m1, m1, 1e-5f)), 1e-5f));
                const float c0 = -m0 * r0, c1 = -m1 * r1;
#pragma unroll
                for (int c = 0; c < 2; c++) {
                    const uint32_t xv = (j & 1) ? x[c][h][j >> 1].y : x[c][h][j >> 1].x;
                    u[c][h][j] = pack2h(fmaf(bf_lo(xv), r0, c0), fmaf(bf_hi(xv), r1, c1));
                }
            }
    }
    TS(8);
    uint32_t X[2][2][8], Y[2][2][8];
    fft_stage(u, wb, w, lane);
    wg_wait<0>();
    TS(9);
    named_bar(1 + wg, 128);
    fft_forward(a1, tw, wb, sb + F_S23, X);
    TS(10);
#pragma unroll
    for (int i = 0; i < 4; i++) a1[i] = ldg_tab(12 + i, t);
    const uint64_t d3 = mkdesc(sb + F_S23 + 4096, 16, 1024, 1);
#pragma unroll
    for (int c = 0; c < 2; c++) {
        wg_wait<1>();
        TS(11 + c);
        uint32_t pr[2][4], pi[2][4];
#pragma unroll
        for (int i = 0; i < 4; i++) {
            const uint32_t er = X[c][0][i], ei = X[c][0][4 + i], orr = X[c][1][i], oi = X[c][1][4 + i];
            const uint32_t ar = KH[c][0][i], ai = KH[c][0][4 + i], br = KH[c][1][i], bi = KH[c][1][4 + i];
            pr[0][i] = hfms(bi, oi, hfma(br, orr, hfms(ai, ei, hmul(ar, er))));
            pi[0][i] = hfma(bi, orr, hfma(br, oi, hfma(ai, er, hmul(ar, ei))));
            pr[1][i] = hfms(ai, oi, hfma(ar, orr, hfms(bi, ei, hmul(br, er))));
            pi[1][i] = hfma(ai, orr, hfma(ar, oi, hfma(bi, er, hmul(br, ei))));
        }
        wg_fence();
        wgmma_h32_rs(Y[c][0], pr[0], d3, 0);
        wgmma_h32_rs(Y[c][1], pr[1], d3 + 4, 0);
        wgmma_h32_rs(Y[c][0], pi[0], d3 + 2, 1);
        wgmma_h32_rs(Y[c][1], pi[1], d3 + 6, 1);
        wg_commit();
    }
    const uint32_t zb = wb + 8192;
#pragma unroll
    for (int c = 0; c < 2; c++) {
        if (c == 0) wg_wait<1>(); else wg_wait<0>();
        TS(13 + c);
        uint32_t zr[2][4], zi[2][4];
#pragma unroll
        for (int p = 0; p < 2; p++)
#pragma unroll
            for (int i = 0; i < 4; i++) {
                const uint32_t r = Y[c][p][i], m = Y[c][p][4 + i], tr = u4(tw[p], i), ti = u4(tw[2 + p], i);
                zr[i & 1][2 * p + (i >> 1)] = hfma(m, ti, hmul(r, tr));
                zi[i & 1][2 * p + (i >> 1)] = hfms(r, ti, hmul(m, tr));
            }
        const int kr = 4 * (mj >> 1) + (mj & 1) + 2 * (mj >> 2), ki = kr ^ 2;
#pragma unroll
        for (int h = 0; h < 2; h++) {
            const uint32_t a = zb + (2 * w + h) * 2048;
            stsm_x4(a + kr * 128 + (((4 * c + mi) ^ (kr & 7)) << 4), zr[h][0], zr[h][1], zr[h][2], zr[h][3]);
            stsm_x4(a + ki * 128 + (((4 * c + mi) ^ (ki & 7)) << 4), zi[h][0], zi[h][1], zi[h][2], zi[h][3]);
        }
    }
    TS(15);
    fence_async_smem();
    TS(16);
    named_bar(1 + wg, 128);
    TS(17);
    float acc[32];
    const uint64_t dz = mkdesc(zb, 4096, 1024, 1);
    wg_fence();
#pragma unroll
    for (int ks = 0; ks < 4; ks++) wgmma_sp64_rs(acc, a1[ks], dz + ks * 256, 0x44EEEE44u, ks > 0);
    wg_commit();
    wg_wait<0>();
    TS(18);
#pragma unroll
    for (int c = 0; c < 2; c++)
#pragma unroll
        for (int p = 0; p < 2; p++) {
            uint32_t r[2][2];
#pragma unroll
            for (int j = 0; j < 2; j++) {
                const float* d = acc + 4 * (4 * c + 2 * p + j);
                const uint32_t y0 = pack2(d[0] + d[2], d[1] + d[3]), y1 = pack2(d[0] - d[2], d[1] - d[3]);
                asm("fma.rn.bf16x2 %0, %1, %2, %3;" : "=r"(r[0][j]) : "r"(y0), "r"(oscale[c]), "r"(j ? x[c][0][p].y : x[c][0][p].x));
                asm("fma.rn.bf16x2 %0, %1, %2, %3;" : "=r"(r[1][j]) : "r"(y1), "r"(oscale[c]), "r"(j ? x[c][1][p].y : x[c][1][p].x));
            }
#pragma unroll
            for (int h = 0; h < 2; h++) *(uint2*)(out + (size_t)(ch0 + c) * XP + 1024 * p + ra[h]) = make_uint2(r[h][0], r[h][1]);
        }
    TS_END(slot);
}

constexpr int OT_SMEM = 120 * 1024;
__global__ void __launch_bounds__(256, 1) out_kernel(const bf16* __restrict__ xT, bf16* __restrict__ out, int slot) {
    constexpr int PITCH = 160 + 8;
    extern __shared__ __align__(1024) char smraw[];
    uint16_t* tile = (uint16_t*)smraw;
    const int tid = threadIdx.x, t0 = (blockIdx.x >> 2) * 64, c0 = (blockIdx.x & 3) * 160;
    TS_DECL;
    TS_BEGIN;
    pdl_wait();
    TS(1);
    uint4 v[5];
#pragma unroll
    for (int i = 0; i < 5; i++) {
        const int id = tid + 256 * i, c = id >> 3, p = (id >> 2) & 1, k = id & 3;
        v[i] = ldg128(xT + (size_t)(c0 + c) * XP + p * 1024 + (t0 >> 1) + 8 * k);
    }
#pragma unroll
    for (int i = 0; i < 5; i++) {
        const int id = tid + 256 * i, c = id >> 3, p = (id >> 2) & 1, k = id & 3;
        uint16_t* t = tile + (16 * k + p) * PITCH + c;
        const uint32_t w[4] = {v[i].x, v[i].y, v[i].z, v[i].w};
#pragma unroll
        for (int j = 0; j < 4; j++) { t[(4 * j) * PITCH] = (uint16_t)w[j]; t[(4 * j + 2) * PITCH] = (uint16_t)(w[j] >> 16); }
    }
    TS(2);
    __syncthreads();
#pragma unroll
    for (int i = 0; i < 5; i++) {
        const int id = tid + 256 * i, r = id / 20, c = id - r * 20;
        stg128(out + (size_t)(t0 + r) * DM + c0 + c * 8, *(const uint4*)(tile + r * PITCH + c * 8));
    }
    if (blockIdx.x == 0 && tid == 0) g_epoch = g_epoch + 1;
    TS_END(slot);
}
typedef CUresult (*EncodeTiledFn)(CUtensorMap*, CUtensorMapDataType, cuuint32_t, void*, const cuuint64_t*, const cuuint64_t*, const cuuint32_t*,
                                  const cuuint32_t*, CUtensorMapInterleave, CUtensorMapSwizzle, CUtensorMapL2promotion, CUtensorMapFloatOOBfill);

static void make_map(EncodeTiledFn enc, CUtensorMap* m, const void* base, int rank, const cuuint64_t* dims, const cuuint64_t* strides,
                     const cuuint32_t* box, CUtensorMapSwizzle sw) {
    cuuint32_t es[3] = {1, 1, 1};
    enc(m, CU_TENSOR_MAP_DATA_TYPE_BFLOAT16, rank, (void*)base, dims, strides, box, es, CU_TENSOR_MAP_INTERLEAVE_NONE, sw,
        sw == CU_TENSOR_MAP_SWIZZLE_128B ? CU_TENSOR_MAP_L2_PROMOTION_L2_128B : CU_TENSOR_MAP_L2_PROMOTION_NONE, CU_TENSOR_MAP_FLOAT_OOB_FILL_NONE);
}

template <typename... KArgs, typename... Args>
static void launch(void (*kern)(KArgs...), int grid, int block, int smem, int cluster, bool pdl, Args... args) {
    cudaLaunchConfig_t cfg = {};
    cfg.gridDim = dim3(grid); cfg.blockDim = dim3(block); cfg.dynamicSmemBytes = smem; cfg.stream = cudaStreamPerThread;
    cudaLaunchAttribute at[2];
    int n = 0;
    if (cluster > 1) { at[n].id = cudaLaunchAttributeClusterDimension; at[n].val.clusterDim.x = cluster; at[n].val.clusterDim.y = 1; at[n].val.clusterDim.z = 1; n++; }
    if (pdl) { at[n].id = cudaLaunchAttributeProgrammaticStreamSerialization; at[n].val.programmaticStreamSerializationAllowed = 1; n++; }
    cfg.attrs = at; cfg.numAttrs = n;
    cudaLaunchKernelEx(&cfg, kern, KArgs(args)...);
}

struct HostState {
    bool ready = false;
    const void* key[4] = {nullptr, nullptr, nullptr, nullptr};
    CUtensorMap mX[2], mRes[2], mW, mWr, mWo, mWor, mOut;
    bf16 *x1T, *x2T;
    float* sums;
};

extern "C" void kernel_launch(void* const* d_in, const int* in_sizes, int n_in, void* d_out, int out_size) {
    const bf16* x = (const bf16*)d_in[0];
    const bf16* wqkv = (const bf16*)d_in[1];
    const bf16* wo = (const bf16*)d_in[2];
    const bf16* lar = (const bf16*)d_in[4];
    const bf16* aim = (const bf16*)d_in[5];
    const bf16* cre = (const bf16*)d_in[6];
    const bf16* cim = (const bf16*)d_in[7];
    const bf16* logdt = (const bf16*)d_in[8];
    const bf16* dskip = (const bf16*)d_in[9];
    static HostState hs;
    if (!hs.ready || hs.key[0] != wqkv || hs.key[1] != wo || hs.key[2] != x) {
        void* fn = nullptr;
        cudaDriverEntryPointQueryResult qr;
        cudaGetDriverEntryPoint("cuTensorMapEncodeTiled", &fn, cudaEnableDefault, &qr);
        EncodeTiledFn enc = (EncodeTiledFn)fn;
        cudaGetSymbolAddress((void**)&hs.x1T, g_x1T);
        cudaGetSymbolAddress((void**)&hs.x2T, g_x2T);
        cudaGetSymbolAddress((void**)&hs.sums, g_sums);
        {
            cuuint64_t d[3] = {DM, SEQ / 2, 2}, s[2] = {DM * 4, DM * 2};
            cuuint32_t b[3] = {64, 64, 2}, br[3] = {16, 64, 2};
            make_map(enc, &hs.mX[0], x, 3, d, s, b, CU_TENSOR_MAP_SWIZZLE_128B);
            make_map(enc, &hs.mRes[0], x, 3, d, s, br, CU_TENSOR_MAP_SWIZZLE_32B);
            cuuint64_t d2[3] = {SEQ / 2, DM, 2}, s2[2] = {XP * 2, SEQ};
            cuuint32_t b2[3] = {64, 80, 2};
            make_map(enc, &hs.mX[1], hs.x2T, 3, d2, s2, b, CU_TENSOR_MAP_SWIZZLE_128B);
            make_map(enc, &hs.mRes[1], hs.x2T, 3, d2, s2, b2, CU_TENSOR_MAP_SWIZZLE_128B);
            cuuint64_t d3[2] = {SEQ, DM};
            make_map(enc, &hs.mOut, hs.x1T, 2, d3, s2, b2, CU_TENSOR_MAP_SWIZZLE_128B);
        }
        { cuuint64_t d[2] = {3 * DM, DM}, s[1] = {3 * DM * 2}; cuuint32_t b[2] = {64, 32};
          make_map(enc, &hs.mW, wqkv, 2, d, s, b, CU_TENSOR_MAP_SWIZZLE_128B); }
        { cuuint64_t d[3] = {DM, DM, 3}, s[2] = {3 * DM * 2, DM * 2}; cuuint32_t b[3] = {16, 32, 3};
          make_map(enc, &hs.mWr, wqkv, 3, d, s, b, CU_TENSOR_MAP_SWIZZLE_32B); }
        { cuuint64_t d[2] = {DM, DM}, s[1] = {DM * 2}; cuuint32_t b[2] = {64, 40}, br[2] = {16, 40};
          make_map(enc, &hs.mWo, wo, 2, d, s, b, CU_TENSOR_MAP_SWIZZLE_128B);
          make_map(enc, &hs.mWor, wo, 2, d, s, br, CU_TENSOR_MAP_SWIZZLE_32B); }
        cudaFuncSetAttribute(attn_kernel, cudaFuncAttributeMaxDynamicSharedMemorySize, Q_SMEM);
        cudaFuncSetAttribute(conv_kernel, cudaFuncAttributeMaxDynamicSharedMemorySize, F_SMEM);
        cudaFuncSetAttribute(out_kernel, cudaFuncAttributeMaxDynamicSharedMemorySize, OT_SMEM);
        hs.key[0] = wqkv; hs.key[1] = wo; hs.key[2] = x;
        hs.ready = true;
    }
    const SsmParams sp = {lar, aim, cre, cim, logdt, dskip};
    for (int l = 0; l < 2; l++) {
        const bf16* xin = l ? hs.x2T : x;
        launch(attn_kernel, 128, 384, Q_SMEM, 2, l > 0, hs.mX[l], hs.mW, hs.mWr, hs.mWo, hs.mWor, hs.mRes[l], hs.mOut, xin, wqkv, wo, hs.sums, sp, l, 2 * l);
        launch(conv_kernel, 107, 384, F_SMEM, 1, true, (const bf16*)hs.x1T, (const float*)(hs.sums + 2 * l * SEQ), hs.x2T, 2 * l + 1);
    }
    launch(out_kernel, 128, 256, OT_SMEM, 1, true, (const bf16*)hs.x2T, (bf16*)d_out, 4);
}
```

```cpp
#include <cuda_runtime.h>
#include <cuda.h>
#include <cuda_bf16.h>
#include <cuda_fp16.h>
#include <stdint.h>

typedef __nv_bfloat16 bf16;

constexpr int SEQ = 2048;
constexpr int DM  = 640;
constexpr int XP  = SEQ + 64;
constexpr int NMODE = 192;

__device__ __forceinline__ uint32_t s2u(const void* p) { return (uint32_t)__cvta_generic_to_shared(p); }
__device__ __forceinline__ void mbar_init(uint32_t b, int c) { asm volatile("mbarrier.init.shared::cta.b64 [%0], %1;" ::"r"(b), "r"(c)); }
__device__ __forceinline__ void mbar_expect(uint32_t b, uint32_t bytes) { asm volatile("mbarrier.arrive.expect_tx.shared::cta.b64 _, [%0], %1;" ::"r"(b), "r"(bytes) : "memory"); }
__device__ __forceinline__ void mbar_arrive(uint32_t b) { asm volatile("mbarrier.arrive.shared::cta.b64 _, [%0];" ::"r"(b) : "memory"); }
__device__ __forceinline__ void mbar_arrive_cta(uint32_t b, uint32_t cta) {
    asm volatile("{\n.reg .b32 ra;\nmapa.shared::cluster.u32 ra, %0, %1;\nmbarrier.arrive.shared::cluster.b64 _, [ra];\n}" ::"r"(b), "r"(cta) : "memory");
}
__device__ __forceinline__ void mbar_wait(uint32_t b, uint32_t ph) {
    asm volatile("{\n.reg .pred p;\n.reg .u32 n;\nmbarrier.try_wait.parity.shared::cta.b64 p, [%0], %1;\n@p bra D;\nmov.u32 n, 0;\n"
                 "W: mbarrier.try_wait.parity.shared::cta.b64 p, [%0], %1;\n@p bra D;\nadd.u32 n, n, 1;\nsetp.lt.u32 p, n, 4194304;\n@p bra W;\ntrap;\nD:\n}"
                 ::"r"(b), "r"(ph) : "memory");
}
__device__ __forceinline__ void fence_mbar_init() { asm volatile("fence.mbarrier_init.release.cluster;" ::: "memory"); }
__device__ __forceinline__ void cluster_sync() { asm volatile("barrier.cluster.arrive.aligned;\nbarrier.cluster.wait.aligned;" ::: "memory"); }
__device__ __forceinline__ void pdl_wait() { asm volatile("griddepcontrol.wait;" ::: "memory"); }
__device__ __forceinline__ void pdl_launch() { asm volatile("griddepcontrol.launch_dependents;" ::: "memory"); }
__device__ __forceinline__ void named_bar(int id, int n) { asm volatile("bar.sync %0, %1;" ::"r"(id), "r"(n) : "memory"); }
__device__ __forceinline__ void fence_async_smem() { asm volatile("fence.proxy.async.shared::cta;" ::: "memory"); }

__device__ __forceinline__ void tma2d(uint32_t dst, const CUtensorMap* m, int c0, int c1, uint32_t bar) {
    asm volatile("cp.async.bulk.tensor.2d.shared::cluster.global.mbarrier::complete_tx::bytes [%0], [%1, {%3, %4}], [%2];"
                 ::"r"(dst), "l"(m), "r"(bar), "r"(c0), "r"(c1) : "memory");
}
__device__ __forceinline__ void tma2d_mc(uint32_t dst, const CUtensorMap* m, int c0, int c1, uint32_t bar, uint16_t mask) {
    asm volatile("cp.async.bulk.tensor.2d.shared::cluster.global.mbarrier::complete_tx::bytes.multicast::cluster [%0], [%1, {%3, %4}], [%2], %5;"
                 ::"r"(dst), "l"(m), "r"(bar), "r"(c0), "r"(c1), "h"(mask) : "memory");
}
__device__ __forceinline__ void tma3d(uint32_t dst, const CUtensorMap* m, int c0, int c1, int c2, uint32_t bar) {
    asm volatile("cp.async.bulk.tensor.3d.shared::cluster.global.mbarrier::complete_tx::bytes [%0], [%1, {%3, %4, %5}], [%2];"
                 ::"r"(dst), "l"(m), "r"(bar), "r"(c0), "r"(c1), "r"(c2) : "memory");
}
__device__ __forceinline__ void tma3d_mc(uint32_t dst, const CUtensorMap* m, int c0, int c1, int c2, uint32_t bar, uint16_t mask) {
    asm volatile("cp.async.bulk.tensor.3d.shared::cluster.global.mbarrier::complete_tx::bytes.multicast::cluster [%0], [%1, {%3, %4, %5}], [%2], %6;"
                 ::"r"(dst), "l"(m), "r"(bar), "r"(c0), "r"(c1), "r"(c2), "h"(mask) : "memory");
}
__device__ __forceinline__ void bulk_g2s(uint32_t dst, const void* src, uint32_t bytes, uint32_t bar) {
    asm volatile("cp.async.bulk.shared::cluster.global.mbarrier::complete_tx::bytes [%0], [%1], %2, [%3];"
                 ::"r"(dst), "l"(src), "r"(bytes), "r"(bar) : "memory");
}
__device__ __forceinline__ void prefetch_l2(const void* p) { asm volatile("prefetch.global.L2 [%0];" ::"l"(p)); }
__device__ __forceinline__ void prefetch_tmap(const CUtensorMap* m) { asm volatile("prefetch.tensormap [%0];" ::"l"(m) : "memory"); }

__device__ __forceinline__ void wg_fence() { asm volatile("wgmma.fence.sync.aligned;" ::: "memory"); }
__device__ __forceinline__ void wg_commit() { asm volatile("wgmma.commit_group.sync.aligned;" ::: "memory"); }
template <int N> __device__ __forceinline__ void wg_wait() { asm volatile("wgmma.wait_group.sync.aligned %0;" ::"n"(N) : "memory"); }
__device__ __forceinline__ uint64_t mkdesc(uint32_t addr, uint32_t lbo, uint32_t sbo, uint32_t mode) {
    return (uint64_t)((addr & 0x3FFFF) >> 4) | ((uint64_t)(lbo >> 4) << 16) | ((uint64_t)(sbo >> 4) << 32) | ((uint64_t)mode << 62);
}

__device__ __forceinline__ void mma16816(float (&c)[4], uint32_t a0, uint32_t a1, uint32_t a2, uint32_t a3, uint32_t b0, uint32_t b1) {
    asm("mma.sync.aligned.m16n8k16.row.col.f32.bf16.bf16.f32 {%0,%1,%2,%3},{%4,%5,%6,%7},{%8,%9},{%0,%1,%2,%3};"
                 : "+f"(c[0]), "+f"(c[1]), "+f"(c[2]), "+f"(c[3]) : "r"(a0), "r"(a1), "r"(a2), "r"(a3), "r"(b0), "r"(b1));
}
__device__ __forceinline__ void mma1688(float (&c)[4], uint32_t a0, uint32_t a1, uint32_t b0) {
    asm("mma.sync.aligned.m16n8k8.row.col.f32.bf16.bf16.f32 {%0,%1,%2,%3},{%4,%5},{%6},{%0,%1,%2,%3};"
                 : "+f"(c[0]), "+f"(c[1]), "+f"(c[2]), "+f"(c[3]) : "r"(a0), "r"(a1), "r"(b0));
}
__device__ __forceinline__ void ldsm_x4(uint32_t& r0, uint32_t& r1, uint32_t& r2, uint32_t& r3, uint32_t a) {
    asm volatile("ldmatrix.sync.aligned.m8n8.x4.shared.b16 {%0,%1,%2,%3}, [%4];" : "=r"(r0), "=r"(r1), "=r"(r2), "=r"(r3) : "r"(a) : "memory");
}
__device__ __forceinline__ void ldsm_x4_t(uint32_t& r0, uint32_t& r1, uint32_t& r2, uint32_t& r3, uint32_t a) {
    asm volatile("ldmatrix.sync.aligned.m8n8.x4.trans.shared.b16 {%0,%1,%2,%3}, [%4];" : "=r"(r0), "=r"(r1), "=r"(r2), "=r"(r3) : "r"(a) : "memory");
}
__device__ __forceinline__ void ldsm_x2(uint32_t& r0, uint32_t& r1, uint32_t a) {
    asm volatile("ldmatrix.sync.aligned.m8n8.x2.shared.b16 {%0,%1}, [%2];" : "=r"(r0), "=r"(r1) : "r"(a) : "memory");
}
__device__ __forceinline__ void ldsm_x2_t(uint32_t& r0, uint32_t& r1, uint32_t a) {
    asm volatile("ldmatrix.sync.aligned.m8n8.x2.trans.shared.b16 {%0,%1}, [%2];" : "=r"(r0), "=r"(r1) : "r"(a) : "memory");
}
__device__ __forceinline__ void stsm_x4(uint32_t a, uint32_t r0, uint32_t r1, uint32_t r2, uint32_t r3) {
    asm volatile("stmatrix.sync.aligned.m8n8.x4.shared.b16 [%0], {%1,%2,%3,%4};" ::"r"(a), "r"(r0), "r"(r1), "r"(r2), "r"(r3) : "memory");
}
__device__ __forceinline__ void stsm_x4_t(uint32_t a, uint32_t r0, uint32_t r1, uint32_t r2, uint32_t r3) {
    asm volatile("stmatrix.sync.aligned.m8n8.x4.trans.shared.b16 [%0], {%1,%2,%3,%4};" ::"r"(a), "r"(r0), "r"(r1), "r"(r2), "r"(r3) : "memory");
}
__device__ __forceinline__ void stsm_x2(uint32_t a, uint32_t r0, uint32_t r1) {
    asm volatile("stmatrix.sync.aligned.m8n8.x2.shared.b16 [%0], {%1,%2};" ::"r"(a), "r"(r0), "r"(r1) : "memory");
}
__device__ __forceinline__ uint32_t movm_t(uint32_t a) {
    uint32_t d;
    asm volatile("movmatrix.sync.aligned.m8n8.trans.b16 %0, %1;" : "=r"(d) : "r"(a));
    return d;
}
__device__ __forceinline__ uint32_t lds32(uint32_t a) { uint32_t v; asm volatile("ld.shared.u32 %0, [%1];" : "=r"(v) : "r"(a) : "memory"); return v; }
__device__ __forceinline__ uint32_t ldsv32(uint32_t a) { uint32_t v; asm volatile("ld.volatile.shared.u32 %0, [%1];" : "=r"(v) : "r"(a) : "memory"); return v; }
__device__ __forceinline__ void sts32(uint32_t a, uint32_t v) { asm volatile("st.shared.u32 [%0], %1;" ::"r"(a), "r"(v) : "memory"); }
__device__ __forceinline__ uint4 lds128(uint32_t a) { uint4 v; asm volatile("ld.shared.v4.u32 {%0,%1,%2,%3}, [%4];" : "=r"(v.x), "=r"(v.y), "=r"(v.z), "=r"(v.w) : "r"(a) : "memory"); return v; }
__device__ __forceinline__ void sts128(uint32_t a, uint4 v) { asm volatile("st.shared.v4.u32 [%0], {%1,%2,%3,%4};" ::"r"(a), "r"(v.x), "r"(v.y), "r"(v.z), "r"(v.w) : "memory"); }

__device__ __forceinline__ void stg128(void* p, uint4 v) { asm volatile("st.global.v4.u32 [%0], {%1,%2,%3,%4};" ::"l"(p), "r"(v.x), "r"(v.y), "r"(v.z), "r"(v.w) : "memory"); }

__device__ __forceinline__ uint4 ldg128(const void* p) { uint4 v; asm volatile("ld.global.v4.u32 {%0,%1,%2,%3}, [%4];" : "=r"(v.x), "=r"(v.y), "=r"(v.z), "=r"(v.w) : "l"(p) : "memory"); return v; }
__device__ __forceinline__ uint2 ldg64(const void* p) { uint2 v; asm volatile("ld.global.v2.u32 {%0,%1}, [%2];" : "=r"(v.x), "=r"(v.y) : "l"(p) : "memory"); return v; }
__device__ __forceinline__ uint32_t ldg32(const void* p) { uint32_t v; asm volatile("ld.global.u32 %0, [%1];" : "=r"(v) : "l"(p) : "memory"); return v; }

__device__ __forceinline__ uint32_t pack2(float lo, float hi) {
    uint32_t r;
    asm("cvt.rn.bf16x2.f32 %0, %1, %2;" : "=r"(r) : "f"(hi), "f"(lo));
    return r;
}
__device__ __forceinline__ float bf_lo(uint32_t v) { return __uint_as_float(v << 16); }
__device__ __forceinline__ float bf_hi(uint32_t v) { return __uint_as_float(v & 0xFFFF0000u); }
__device__ __forceinline__ float rbf(float x) { return __uint_as_float(pack2(0.f, x) & 0xFFFF0000u); }
__device__ __forceinline__ float ex2(float x) { float r; asm("ex2.approx.ftz.f32 %0, %1;" : "=f"(r) : "f"(x)); return r; }

__device__ __forceinline__ float2 ln_finish(float sum, float sumsq) {
    const float m = sum * (1.0f / DM);
    const float v = fmaxf(fmaf(sumsq, 1.0f / DM, -m * m), 0.f);
    float s, r;
    asm("sqrt.approx.ftz.f32 %0, %1;" : "=f"(s) : "f"(rbf(rbf(v) + 1e-5f)));
    asm("rcp.approx.ftz.f32 %0, %1;" : "=f"(r) : "f"(rbf(s)));
    return make_float2(m, r);
}
__device__ __forceinline__ uint32_t ln_finish_packed(float sum, float sumsq) {
    const float m = sum * (1.0f / DM);
    const float v = fmaxf(fmaf(sumsq, 1.0f / DM, -m * m), 0.f);
    float s;
    asm("sqrt.approx.ftz.f32 %0, %1;" : "=f"(s) : "f"(rbf(rbf(v) + 1e-5f)));
    return pack2(s, m);
}
__device__ __forceinline__ float frsq(float x) { float r; asm("rsqrt.approx.ftz.f32 %0, %1;" : "=f"(r) : "f"(x)); return r; }
__device__ __forceinline__ float frcp(float x) { float r; asm("rcp.approx.ftz.f32 %0, %1;" : "=f"(r) : "f"(x)); return r; }
__device__ __forceinline__ bool elect_one() {
    uint32_t p;
    asm volatile("{\n.reg .pred p;\nelect.sync _|p, 0xffffffff;\nselp.u32 %0, 1, 0, p;\n}" : "=r"(p));
    return p != 0;
}
__device__ __forceinline__ void cluster_arrive_relaxed() { asm volatile("barrier.cluster.arrive.relaxed.aligned;" ::: "memory"); }
__device__ __forceinline__ void cluster_wait() { asm volatile("barrier.cluster.wait.aligned;" ::: "memory"); }
__device__ __forceinline__ unsigned long long ld_ll(const unsigned long long* p) {
    unsigned long long v;
    asm volatile("ld.relaxed.gpu.global.b64 %0, [%1];" : "=l"(v) : "l"(p) : "memory");
    return v;
}
__device__ __forceinline__ void st_ll(unsigned long long* p, uint32_t payload, uint32_t tag) {
    const unsigned long long v = (unsigned long long)payload | ((unsigned long long)tag << 32);
    asm volatile("st.relaxed.gpu.global.b64 [%0], %1;" ::"l"(p), "l"(v) : "memory");
}
__device__ __forceinline__ uint4 ld_ll4(const uint4* p) {
    uint4 v;
    asm volatile("{\n.reg .b128 t;\n.reg .b64 a, b;\nld.relaxed.gpu.global.b128 t, [%4];\nmov.b128 {a, b}, t;\nmov.b64 {%0, %1}, a;\nmov.b64 {%2, %3}, b;\n}"
                 : "=r"(v.x), "=r"(v.y), "=r"(v.z), "=r"(v.w) : "l"(p) : "memory");
    return v;
}
__device__ __forceinline__ void st_ll4(uint4* p, uint32_t x, uint32_t y, uint32_t z, uint32_t w) {
    asm volatile("{\n.reg .b128 t;\n.reg .b64 a, b;\nmov.b64 a, {%1, %2};\nmov.b64 b, {%3, %4};\nmov.b128 t, {a, b};\nst.relaxed.gpu.global.b128 [%0], t;\n}"
                 ::"l"(p), "r"(x), "r"(y), "r"(z), "r"(w) : "memory");
}

__device__ __forceinline__ void bulk_s2g(void* dst, uint32_t src, uint32_t bytes) {
    asm volatile("cp.async.bulk.global.shared::cta.bulk_group [%0], [%1], %2;" ::"l"(dst), "r"(src), "r"(bytes) : "memory");
}
__device__ __forceinline__ void bulk_commit() { asm volatile("cp.async.bulk.commit_group;" ::: "memory"); }
__device__ __forceinline__ void bulk_wait() { asm volatile("cp.async.bulk.wait_group 0;" ::: "memory"); }
__device__ __forceinline__ void fence_async_global() { asm volatile("fence.proxy.async.global;" ::: "memory"); }
__device__ __forceinline__ void fence_release() { asm volatile("fence.release.gpu;" ::: "memory"); }
__device__ __forceinline__ void fence_acquire() { asm volatile("fence.acquire.gpu;" ::: "memory"); }
template<int TA, int TB>
__device__ __forceinline__ void wgmma_n192(float (&d)[96], uint64_t da, uint64_t db, int scale_d) {
  asm volatile("{\n.reg .pred p;\nsetp.ne.b32 p, %98, 0;\n"
    "wgmma.mma_async.sync.aligned.m64n192k16.f32.bf16.bf16 "
    "{%0, %1, %2, %3, %4, %5, %6, %7, %8, %9, %10, %11, %12, %13, %14, %15, %16, %17, %18, %19, %20, %21, %22, %23, %24, %25, %26, %27, %28, %29, %30, %31, %32, %33, %34, %35, %36, %37, %38, %39, %40, %41, %42, %43, %44, %45, %46, %47, %48, %49, %50, %51, %52, %53, %54, %55, %56, %57, %58, %59, %60, %61, %62, %63, %64, %65, %66, %67, %68, %69, %70, %71, %72, %73, %74, %75, %76, %77, %78, %79, %80, %81, %82, %83, %84, %85, %86, %87, %88, %89, %90, %91, %92, %93, %94, %95}, %96, %97, p, 1, 1, %99, %100;\n}\n"
    : "+f"(d[0]), "+f"(d[1]), "+f"(d[2]), "+f"(d[3]), "+f"(d[4]), "+f"(d[5]), "+f"(d[6]), "+f"(d[7]), "+f"(d[8]), "+f"(d[9]), "+f"(d[10]), "+f"(d[11]), "+f"(d[12]), "+f"(d[13]), "+f"(d[14]), "+f"(d[15]), "+f"(d[16]), "+f"(d[17]), "+f"(d[18]), "+f"(d[19]), "+f"(d[20]), "+f"(d[21]), "+f"(d[22]), "+f"(d[23]), "+f"(d[24]), "+f"(d[25]), "+f"(d[26]), "+f"(d[27]), "+f"(d[28]), "+f"(d[29]), "+f"(d[30]), "+f"(d[31]), "+f"(d[32]), "+f"(d[33]), "+f"(d[34]), "+f"(d[35]), "+f"(d[36]), "+f"(d[37]), "+f"(d[38]), "+f"(d[39]), "+f"(d[40]), "+f"(d[41]), "+f"(d[42]), "+f"(d[43]), "+f"(d[44]), "+f"(d[45]), "+f"(d[46]), "+f"(d[47]), "+f"(d[48]), "+f"(d[49]), "+f"(d[50]), "+f"(d[51]), "+f"(d[52]), "+f"(d[53]), "+f"(d[54]), "+f"(d[55]), "+f"(d[56]), "+f"(d[57]), "+f"(d[58]), "+f"(d[59]), "+f"(d[60]), "+f"(d[61]), "+f"(d[62]), "+f"(d[63]), "+f"(d[64]), "+f"(d[65]), "+f"(d[66]), "+f"(d[67]), "+f"(d[68]), "+f"(d[69]), "+f"(d[70]), "+f"(d[71]), "+f"(d[72]), "+f"(d[73]), "+f"(d[74]), "+f"(d[75]), "+f"(d[76]), "+f"(d[77]), "+f"(d[78]), "+f"(d[79]), "+f"(d[80]), "+f"(d[81]), "+f"(d[82]), "+f"(d[83]), "+f"(d[84]), "+f"(d[85]), "+f"(d[86]), "+f"(d[87]), "+f"(d[88]), "+f"(d[89]), "+f"(d[90]), "+f"(d[91]), "+f"(d[92]), "+f"(d[93]), "+f"(d[94]), "+f"(d[95])
    : "l"(da), "l"(db), "r"(scale_d), "n"(TA), "n"(TB));
}

template<int TA, int TB>
__device__ __forceinline__ void wgmma_n48(float (&d)[24], uint64_t da, uint64_t db, int scale_d) {
  asm volatile("{\n.reg .pred p;\nsetp.ne.b32 p, %26, 0;\n"
    "wgmma.mma_async.sync.aligned.m64n48k16.f32.bf16.bf16 "
    "{%0, %1, %2, %3, %4, %5, %6, %7, %8, %9, %10, %11, %12, %13, %14, %15, %16, %17, %18, %19, %20, %21, %22, %23}, %24, %25, p, 1, 1, %27, %28;\n}\n"
    : "+f"(d[0]), "+f"(d[1]), "+f"(d[2]), "+f"(d[3]), "+f"(d[4]), "+f"(d[5]), "+f"(d[6]), "+f"(d[7]), "+f"(d[8]), "+f"(d[9]), "+f"(d[10]), "+f"(d[11]), "+f"(d[12]), "+f"(d[13]), "+f"(d[14]), "+f"(d[15]), "+f"(d[16]), "+f"(d[17]), "+f"(d[18]), "+f"(d[19]), "+f"(d[20]), "+f"(d[21]), "+f"(d[22]), "+f"(d[23])
    : "l"(da), "l"(db), "r"(scale_d), "n"(TA), "n"(TB));
}

__device__ __forceinline__ void wgmma_rs64(float (&d)[32], const uint4& a, uint64_t db, int scale_d) {
  asm volatile("{\n.reg .pred p;\nsetp.ne.b32 p, %37, 0;\n"
    "wgmma.mma_async.sync.aligned.m64n64k16.f32.bf16.bf16 {%0,%1,%2,%3,%4,%5,%6,%7,%8,%9,%10,%11,%12,%13,%14,%15,%16,%17,%18,%19,%20,%21,%22,%23,%24,%25,%26,%27,%28,%29,%30,%31}, {%32,%33,%34,%35}, %36, p, 1, 1, 1;\n}\n"
    : "+f"(d[0]), "+f"(d[1]), "+f"(d[2]), "+f"(d[3]), "+f"(d[4]), "+f"(d[5]), "+f"(d[6]), "+f"(d[7]), "+f"(d[8]), "+f"(d[9]), "+f"(d[10]), "+f"(d[11]), "+f"(d[12]), "+f"(d[13]), "+f"(d[14]), "+f"(d[15]), "+f"(d[16]), "+f"(d[17]), "+f"(d[18]), "+f"(d[19]), "+f"(d[20]), "+f"(d[21]), "+f"(d[22]), "+f"(d[23]), "+f"(d[24]), "+f"(d[25]), "+f"(d[26]), "+f"(d[27]), "+f"(d[28]), "+f"(d[29]), "+f"(d[30]), "+f"(d[31])
    : "r"(a.x), "r"(a.y), "r"(a.z), "r"(a.w), "l"(db), "r"(scale_d));
}

__device__ __forceinline__ void wgmma_rs16(float (&d)[8], const uint4& a, uint64_t db, int scale_d) {
  asm volatile("{\n.reg .pred p;\nsetp.ne.b32 p, %13, 0;\n"
    "wgmma.mma_async.sync.aligned.m64n16k16.f32.bf16.bf16 {%0,%1,%2,%3,%4,%5,%6,%7}, {%8,%9,%10,%11}, %12, p, 1, 1, 1;\n}\n"
    : "+f"(d[0]), "+f"(d[1]), "+f"(d[2]), "+f"(d[3]), "+f"(d[4]), "+f"(d[5]), "+f"(d[6]), "+f"(d[7])
    : "r"(a.x), "r"(a.y), "r"(a.z), "r"(a.w), "l"(db), "r"(scale_d));
}

__device__ const __align__(1024) uint32_t c_fft[11264] = {
0x2ddc2dba,0x2fe62eb5,0x2ed02eb5,0xafffaf6e,0x2e1f2dfe,0x2e3f2fbc,0x2f022ee9,0xad27af30,0x2e5e2e3f,0x1fd92b5e,0x2f302f1a,0x244ea875,0x2e992e7c,0xad96a993,0x2f5a2f46,0x2e992c32,
0xad00ad72,0xa17eac32,0xa17ea515,0xabb79cb6,0xac07ac87,0x2dfe29f1,0x1fd99648,0xafedae99,0xa9f1ab05,0x2fd42fbc,0x26a1244e,0xad96af91,0xa765a8d5,0x2aaa2e3f,0x29932875,0x2515a8d5,
0xae99adfe,0xb000aee9,0xaf6eafbc,0x2c872f30,0xaf80af1a,0xac32af02,0xae7caf02,0xaaaa217e,0xaff4afc9,0x2b5e9cb6,0xad27addc,0xaff4ae7c,0xafedb000,0x2ffc2eb5,0xab05ac5d,0xacd8af5a,
0x2c072d27,0x9fd92bb7,0xadfead00,0x2fed2e1f,0x25db2993,0xaf6eacb0,0xaf6eaed0,0x2c5d2f46,0xa5151648,0xaddcafdd,0xafffafd4,0xac321648,0xabb7a934,0x28d5a814,0xafa0afed,0xaff4af30,
0x2f302e3f,0x2fed2f1a,0x28142b5e,0x2934a875,0x30002fc9,0x26a12ddc,0xa5db1cb6,0x30002e7c,0x2f462fd4,0xaed0aa4e,0xacb0aa4e,0x29932e99,0x2d272e5e,0xae3faffc,0xaf02adfe,0xae1fa814,
0xa9f1acd8,0x26a1ab05,0x2fd42ffc,0xad96afed,0x2515a30e,0x2fff2e1f,0x2ddc2f1a,0x2c32a30e,0x2d272aaa,0x28752e7c,0x28752c32,0x2fa02f80,0x2f912e99,0xaee9a9f1,0xa8141648,0x9fd92c87,
0xafa0ae7c,0xafafaf46,0x2d002993,0xafa0ac32,0xaf91b000,0x244eac5d,0x2fbc2eb5,0xab05af5a,0xac87ae5e,0x30002dfe,0x2f6e2ffc,0x2e992814,0x1cb6a875,0x25152e1f,0x2c322e1f,0x2d722ff4,
0x27652c87,0xa9932a4e,0xaaaaadba,0xa5152c87,0xabb7a44e,0xafa0af30,0x28d59fd9,0xaff4ae5e,0xaf91ae1f,0x2814abb7,0x2ee92d00,0x1fd9ad27,0xaf5aafff,0x2fd42ed0,0x2fd42fe6,0x30002ddc,
0x2f462f6e,0x2c322fdd,0x2e7c2fdd,0xa993b000,0xab5e2934,0xafafacd8,0xad00244e,0x2f1a2dfe,0xaee9afaf,0x2f30a17e,0xadfeaff8,0xafbca30e,0x2c5da765,0xa9f12ddc,0x2d969cb6,0x2c5dacb0,
0x2bb7a993,0x2f1aa515,0x2f1a2765,0xaff4aaaa,0x2e5e2fd4,0xab052dba,0x29342f6e,0x2ee9a6a1,0xadba1fd9,0xa5dbafed,0xafddac07,0xaa4e2dfe,0xacb0aff8,0x2ddc2f02,0x9cb6ae3f,0xa765aff8,
0xaeb5af91,0xaa4eafed,0x9648ae5e,0xac5d2d4d,0x2ddca17e,0x2e7c2e3f,0x2fc92e3f,0x1cb6afa0,0x2bb72fe6,0xaff8a993,0xab5e2aaa,0x2bb72fc9,0xafbcaa4e,0x2f30a5db,0xadfeafdd,0xaee9adba,
0xacd828d5,0xaf91230e,0xaf30af02,0x2c072fa0,0xac5dafff,0x2dbaac32,0x2dbaa515,0xae99addc,0x2fc929f1,0xa9932eb5,0x2aaa2fdd,0x2fe629f1,0xa30e2dfe,0xa17eafed,0xaff8ac07,0xafaf1fd9,
0x2dfe2faf,0x28142ff8,0xae5e217e,0x2ffc230e,0xaf5aa515,0xac87af46,0xa6a1af80,0xaf5a2765,0x1cb6ae99,0x2e7c2dba,0x2fc92dba,0x2ddcac5d,0x2f1a2ee9,0xafafab05,0xad002934,0xab5e2e5e,
0x2dbaa814,0x2fdd9fd9,0x25db2f91,0x2a4eaee9,0x27652faf,0xaf4628d5,0xaf80ae1f,0xa5152faf,0xafa0addc,0x2e3fac32,0x2e3fa515,0xa17eafff,0x2dfea6a1,0xacd82dba,0x244e2f6e,0x29342fd4,
0xad27afc9,0xa30eafff,0x2faf2d72,0xad27ae7c,0x2ffc2a4e,0x28142fdd,0xae5e25db,0x2dfe2dba,0xac5d2c07,0xaa4eaf91,0x9648af30,0xaeb5acd8,0xa993aff4,0x2c322f1a,0x2e7c2f1a,0x2f462bb7,
0xae7c26a1,0xafff1648,0x2d72aa4e,0xafc926a1,0x230eaee9,0x2ff89fd9,0x217e2f91,0x2fafa814,0x2d4d2fa0,0xafed230e,0xae5eaf02,0xaf9128d5,0xb000aaaa,0x2fdda515,0x2fdd2765,0x2f6ea993,
0x9cb63000,0xacb02fd4,0xa7652fd4,0x2ddcaf5a,0x217eaffc,0x2ff4ac07,0x2875afbc,0xaff82934,0xa44e2ff4,0xadfea8d5,0xa9342fa0,0x2cd82bb7,0x25dbafe6,0x16482f46,0x29f1af80,0x25dbafc9,
0x2ff41cb6,0x2e1f2765,0x2e1f2cb0,0xa875addc,0xafbca5db,0x1fd9af5a,0xad4dad96,0xacd82fdd,0x2f5a2934,0xaeb52ee9,0x2c5d2e5e,0x3000ab05,0xaed0ab5e,0x2f80a30e,0xaaaaaf02,0xacb0ab5e,
0x25dbaffc,0x2d96afbc,0x2f5aac07,0xafdd2934,0xaaaa2fa0,0xafc92875,0xafe62875,0x29932d27,0x2d00aed0,0x28d52d72,0x2ff89cb6,0x2d00afe6,0xae5e2d96,0x2d4dafd4,0xaf91a6a1,0xafed29f1,
0xafbca17e,0xad4da875,0x1fd9aff4,0xacd82ff8,0x2e992aaa,0xaa4e2fe6,0xaa4e2fc9,0x2fd4a993,0xacb0ad96,0x2fffac87,0x2d72aeb5,0xa765ad96,0x28752f30,0xab5eac07,0xaf1a2cd8,0xae3f2f91,
0xa9342ff4,0xae5e2fa0,0xaee9a8d5,0x2b052bb7,0x2d96aed0,0x2eb59cb6,0x2c872d72,0x2d96afe6,0xaf802c5d,0x2765af6e,0xa515af6e,0xaf4625db,0x2ff8a44e,0xaff42d4d,0xa8752ffc,0xa17e2ee9,
0x2f5a244e,0x2c5d2934,0xaeb52dfe,0x3000acd8,0xacb0ad00,0x2d72aff8,0x2fffa8d5,0xa765ad00,0x217e2f80,0xaf022515,0xaf02a765,0xaf1a2f46,0x2b05afdd,0xa8142f5a,0x2c072d96,0x2d4d25db,
0x2b5eafe6,0x2f02af80,0x230e2f46,0x2b5eafc9,0xaf302d96,0xacd8a6a1,0x2c07afd4,0xaf9129f1,0x2fdda44e,0xad962ffc,0xaf5a2d4d,0xa5db2ee9,0xad72abb7,0x2e7ca17e,0x2fc9a17e,0x2fffad00,
0xaed0a5db,0xaaaaa9f1,0x2f809648,0xacb0a5db,0x28752e5e,0xaf1a2f91,0xab5ead4d,0xae3f2fed,0x2b05aff8,0x2c072875,0xa8142ff4,0x2d4d217e,0xaf6e2d72,0x2eb5afc9,0x2eb5ae7c,0x2dbaafff,
0xaf802f5a,0xafc92e99,0xafe62e99,0x2f46ad96,0x28d52b05,0xaf022fed,0x230e2cd8,0x2fa0affc,0x2fbcaf02,0xa9342d27,0x2ffcae1f,0x2c07ae3f,0xa6a1ac32,0x2a4e9cb6,0x9648ad72,0xa6a1a515,
0x28752aaa,0xa8d52cb0,0xa8d52ed0,0x2e3faf80,0x2fedaeb5,0x29349648,0x2f30aa4e,0x2814ac5d,0x1648ad4d,0x2e99acd8,0x2c87afbc,0xa9f11fd9,0xafe62d27,0x2fffafaf,0xaddc230e,0xaed02d27,
0x2fd4af30,0x2f6eae5e,0x2dbaa44e,0xa6a19fd9,0x1cb6ad27,0x2fe6aff4,0x2ed0aff4,0xad722b5e,0xafaf2cb0,0x2e1faf46,0xa8d5a993,0xafaf2ed0,0xac072f6e,0x2934ac87,0xaffc2e99,0xafbc3000,
0xa44eab5e,0x2b05ad00,0x2f91afaf,0xafbc2f1a,0xafd42d72,0x1648a765,0x1648acb0,0xafdd2fff,0xac322f5a,0xaaaa26a1,0xaf802c87,0xae7c2f5a,0x2d009fd9,0xae1f2cd8,0xad272fbc,0xabb72d4d,
0xaffc2f02,0xaee92e1f,0x244ead27,0xad4d2e3f,0xa9f12e7c,0xafdd2f80,0xaeb52aaa,0xa9f12c32,0x2d72a5db,0xafe63000,0xaed03000,0x9cb626a1,0x2fa0afbc,0xaf022f91,0x230e2b05,0x28d5a44e,
0x96482c07,0xac872d4d,0xae992b05,0x29f1a814,0x2ed0abb7,0xa9932b5e,0xaf462ff8,0x2cb0abb7,0x2f1aafff,0xa30e2765,0xa30e2cb0,0x2e1fad72,0x1fd9ac5d,0x244e9648,0x2e5eaa4e,0x2f30aeb5,
0x2ff8aed0,0x2e3faddc,0xaf022fff,0x2ff8afe6,0x2d4daf6e,0x2ee9ae99,0xa44e2c87,0x2ffcb000,0xa6a1a814,0x2f6eaf30,0x2dbaa934,0x2fd4afed,0xaf462d00,0x2fc9afa0,0x2fe6afa0,0x2f80afaf,
0x2515ac5d,0x2d72ad96,0x1cb629f1,0x2c32ac5d,0xad002814,0x2d27ad4d,0x2e1fab05,0x2bb7ac07,0xaffc2f1a,0x2cd8ad00,0x2fedafaf,0x2b05ab5e,0xadba2f80,0x2c87acb0,0x2c87aed0,0x2a4eaaaa,
0x2f802f6e,0x2fc92fdd,0x2fe62fdd,0xaf46b000,0x2fa02f91,0x2bb72e5e,0x2ff42fed,0xa8d5ad4d,0x2fbc2faf,0xa934217e,0x2ffc2ff8,0x2c07230e,0x2fd42fc9,0xaf5aad72,0x30002fff,0x2fd42e7c,
0x2bb72aaa,0x2f1a2cb0,0x2f1a2ed0,0xaff4af80,0x2cd82c5d,0x2f303000,0x2f912f5a,0xac07aeb5,0x2dba2d4d,0x25db2cd8,0x2fdd2fbc,0x2a4e9fd9,0x2e7c2e1f,0xad72a875,0x2fff2ff4,0x2fc92e1f,
0xa6a1a934,0x29f1a44e,0x2d962cd8,0xafd4adfe,0x1cb6a17e,0x2fe62e3f,0x2ed02e3f,0xad72afa0,0x28752515,0x2d272f80,0x2fa02f46,0x2875a765,0x2c072a4e,0xa93425db,0x2ffc2fdd,0x2fbc2dba,
0xae5eaf1a,0xa934ae3f,0x2b052875,0xaee9ab5e,0xac5dad72,0x2dba2765,0x2dba2cb0,0xae99afff,0xa765aa4e,0x2f802fd4,0x2f462e99,0x2515aa4e,0x230e9fd9,0x217e2cd8,0x2ff82fbc,0x2faf2d4d,
0xaffcafaf,0xaee9aff8,0x244ea17e,0xad4da30e,0xaf6eafe6,0x25dbaaaa,0x2c5d2993,0xaf6eafc9,0xad72ae99,0x2fe62dba,0x2ed02dba,0x1cb6ac5d,0xa8d5ac07,0x2bb72f30,0x2ff42f91,0x2fa02cd8,
0xadbaac07,0xafddad4d,0xa5dbab05,0xaa4e2814,0xafc9af02,0xaaaaaf1a,0x2993217e,0xafe6af02,0xafa0afff,0x2e3f2765,0x2e3f2cb0,0xa17ead72,0xad4daeb5,0x2e5e3000,0x2fed2f5a,0x2f912c5d,
0xa17e2765,0xad001cb6,0xabb7addc,0xa17e2cb0,0xad4daa4e,0xaee9afdd,0x244ea5db,0xaffcadba,0xafd4aee9,0x29f1a934,0x2d962b05,0xa6a1ae5e,0xaf46aff4,0x2fc92f1a,0x2fe62f1a,0x2f802bb7,
0x2cb02eb5,0x1cb62dba,0xaddcaf6e,0x27652eb5,0xa30e2814,0xaff8ad4d,0xa17eab05,0xafafac07,0xadfeab5e,0xa44eae3f,0x2cd82875,0xa934af1a,0xb000af80,0x2fdd2cb0,0x2fdd2ed0,0x2f6e2aaa,
0x2d723000,0x25152fd4,0x2c322fd4,0x1cb6af5a,0xae1f9fd9,0xae3faee9,0xaf02a814,0x2d272f91,0xacd8aff4,0x2ffc28d5,0xab05afa0,0xafedabb7,0x2e992515,0xad962aaa,0x2f5a2993,0x2e99a765,
0x2ff42ddc,0x2e1f2ed0,0x2e1f2fe6,0xa875afff,0xa8142c87,0xaffca9f1,0xadfe1648,0x2e5e2e99,0xaf5aaf30,0x2eb5a814,0xac5dafed,0xb000a934,0x2c32a8d5,0xa9932e3f,0x2f462875,0x2e7ca8d5,
0x2e991fd9,0x30002814,0x2f6e2ee9,0xac87af91,0x29932fa0,0xaed02875,0xacb02875,0x2f462d27,0xaff4ac32,0x2b5eaddc,0xad27afff,0xaff4a515,0x244ead96,0x1fd92fd4,0x2f3026a1,0x2e5ea9f1,
0x2814ad27,0x2dfeabb7,0x2ffc2d00,0xae5eae1f,0x2e992f80,0xaa4e2e7c,0xaa4e2c32,0x2fd42aaa,0xae7c1648,0x9cb6afdd,0xaddcafd4,0xafc91648,0xa875af91,0x2b5e2fbc,0x2f1a244e,0x2e3fab05,
0xab05aff4,0x244eafa0,0x2fbc28d5,0xaf91abb7,0x30002c32,0x26a12fff,0xa5db2ddc,0x30002515,0xaaaa2c5d,0xac32af6e,0xae7caf6e,0xaf8025db,0xad27afed,0x2e3f2dfe,0x2f021fd9,0x2e1fac07,
0xaf5aae5e,0xac5daf30,0x2eb59fd9,0xb000a44e,0x2e7ca30e,0x2ddc2e1f,0x1cb62f1a,0x2fc9a30e,0x217e2f46,0xaf02acb0,0xaf02aed0,0xaf1a2993,0xaf30ae99,0x2fbc29f1,0x2ee99648,0x2dfeac87,
0xafa0a515,0xafafa993,0x2d00aaaa,0xafa02765,0x2934ad96,0x2fed26a1,0x28142fd4,0x2f30a9f1,0x2c872fed,0xb0009fd9,0xaf6eadfe,0xae992c07,0xafffabb7,0x2fe6a17e,0x2ed0a17e,0x2ddcad00,
0xac322c87,0xaf462a4e,0x2993adba,0xae7c2c87,0xa875afed,0x2f1aab05,0x2b5e2ffc,0x2e3facd8,0x2f302e1f,0xaee92bb7,0xafbcad00,0xadfe2d27,0xaf6e9cb6,0x2eb5ac32,0x2eb5a515,0x2dbaad72,
0xaaaa2f5a,0xaed02e99,0xacb02e99,0x2f80ad96,0x2b5eaf30,0x2fafa44e,0x2d00ae5e,0xaf1a9fd9,0xac072f02,0xab05ad27,0xad4d2e1f,0x28142e3f,0x2c5daed0,0xa9f12fff,0x2d96addc,0x2c5dafe6,
0x28752f80,0xa8d52fe6,0xa8d52fc9,0x2e3faf46,0xa44eafd4,0x2f91adba,0x2b05af6e,0xafbc26a1,0x96482ffc,0xae99a44e,0xac872ee9,0x29f12d4d,0x2515aff8,0x1cb62f02,0x2d72ae3f,0x2c32aff8,
0x2eb52b05,0x2a4e2cd8,0x16482fed,0x2c5daffc,0xad72ad27,0x2cb0aff4,0x2765aff4,0xafff2b5e,0x2bb72e7c,0xaff82aaa,0xab5e2f80,0x2bb72c32,0xa814af6e,0x2b052c87,0x2d4dae99,0x2c07b000,
0x2feda8d5,0x2f30a30e,0x29342f02,0x2814afa0,0xafd49cb6,0x1648aed0,0x1648afe6,0xafdd2d72,0x2ed029f1,0xaf462eb5,0xa9932fdd,0x2cb029f1,0xad00ad4d,0x2e1f244e,0x2d27aee9,0x2bb7affc,
0x2d4daf02,0x2fbcae1f,0x2cd82d27,0x9fd9ae3f,0xaf5a2cb0,0xac87a993,0xa6a1af46,0xaf5a2ed0,0x2fffa5db,0xacb03000,0xa7653000,0x2d7226a1,0xaf1aa814,0x2fafa934,0x2d00af30,0x2b5eafed,
0x1648afbc,0x2c87affc,0x2e992934,0xa9f1ac07,0xac322faf,0xaf8028d5,0xaaaaae1f,0xae7c2faf,0x2f1aad72,0xa30e2ed0,0xa30e2fe6,0x2e1f1cb6,0xaffc26a1,0x2fedadba,0x2cd8af6e,0x2b05afd4,
0xad27ac32,0xa30ead72,0x2faf9cb6,0xad27a515,0x1fd92f6e,0xafbc2e99,0xacd8ac87,0xad4d3000,0x2c5dafbc,0x2a4e2b05,0x16482f91,0x2eb5a44e,0xaf802d00,0x2ed0afa0,0x2cb0afa0,0x2aaaafaf,
0xafe626a1,0xaddc1648,0x2fffaa4e,0xaed026a1,0x2d002c07,0xad272ffc,0xae1fa934,0xabb72fbc,0x1fd9afa0,0x2e5ea30e,0x244e2f02,0x2f30a8d5,0xadba2f46,0x2c87afe6,0x2c87afc9,0x2a4eaf80,
0xafff2d96,0xae7c2c5d,0xafc92c5d,0x2d72a9f1,0xa17e2dfe,0xaff42fbc,0xa8752ee9,0x2ff8af30,0x2fedad00,0xad4d2f1a,0x2f91ab5e,0x2e5eafaf,0x25dbae7c,0x16482993,0x29f1af46,0x25dbac32,
0xae3f2fff,0xaff82fc9,0xaff82e7c,0x2f02ad72,0x2c0725db,0xadfe2f5a,0x9fd92d96,0x2fedafdd,0x2f6eaf91,0xa6a12c07,0x2fd4acd8,0x2dbaaf30,0xa765ab5e,0x2aaaa30e,0x2993af02,0x2515ab5e,
0xa5db2dfe,0xad962ee9,0xaf5a2fbc,0x2fddaf30,0x2f46ab5e,0xa7652bb7,0x25152bb7,0x2f80aff8,0x2d00afc9,0x28d59cb6,0x2ff8addc,0x2d00ae7c,0xacd89648,0x2dfeac5d,0x2934aeb5,0x244eaa4e,
0x2c07217e,0x9fd92875,0xadfe2ff4,0x2fedaff8,0x2fddaf46,0x29f1a515,0x29f12765,0x2eb5af80,0x2515ad96,0x2ddcac87,0x2fffaeb5,0x2c32ad96,0xaf022b05,0x2fa0aee9,0x28d5ae5e,0x230ea934,
0x2f91ad00,0x2cd8ab5e,0xac072f1a,0x2f30afaf,0x2d96afc9,0x2eb5addc,0x2c879cb6,0x2d96ae7c,0xa993a6a1,0x2fc9af5a,0x2fe6af5a,0x2aaaac87,0xaff82e5e,0x2ff4affc,0x2875adfe,0x217ea814,
0x2f6eafed,0x2fd4af91,0xa6a12d4d,0x2dbaae5e,0x2515ad00,0x2fffaff8,0x2ddca8d5,0x2c32ad00,0xae1f2993,0x2fafafe6,0x2fafafc9,0x28d5aaaa,0xaf912fdd,0x2ee9af5a,0x2814ad96,0x1fd9a5db,
0x2b5eae7c,0x2f02af46,0x230e2993,0x2b5eac32,0xab059648,0x2e5eaeb5,0x2ee9ac5d,0x2934aa4e,0xafdd2e5e,0x2d96adfe,0x2f5aaffc,0x25dba814,0xaddc2faf,0x2cb0ad27,0x2765ad27,0x1cb6a30e,
0xa765a5db,0x2993a9f1,0x2aaa9648,0x2515a5db,0xaf022cd8,0x28d5a934,0x2fa0adfe,0x230ea44e,0xaf912ff8,0x2814a875,0x2ee9aff4,0x1fd9a17e,0xaa4e2ddc,0x26a1a765,0x26a1acb0,0x16489cb6,
0x2d722d96,0x25152c5d,0x2c322c5d,0x1cb6a9f1,0x2d272d4d,0xad00a814,0x2bb72c07,0x2e1f2b05,0x2cd82d00,0xaffcaf1a,0x2b052b5e,0x2fed2faf,0x2c872cb0,0xadbaaf80,0x2a4e2aaa,0x2c872ed0,
0x2e3f2ddc,0x2ff82ed0,0x2ff82fe6,0xaf02afff,0x2ee92e99,0x2d4d2f6e,0x2ffc3000,0xa44eac87,0x2f6e2f30,0xa6a12814,0x2fd42fed,0x2dba2934,0x2fc92fa0,0xaf46ad00,0x2f802faf,0x2fe62fa0,
0xac87ad4d,0x9648ac07,0x29f12814,0xae99ab05,0xa993ab5e,0x2ed02bb7,0x2cb02bb7,0xaf46aff8,0xa30ea765,0x2f1a2fff,0x2e1f2d72,0xa30eacb0,0x244e1648,0x1fd92c5d,0x2f302eb5,0x2e5e2a4e,
0xaee9ae1f,0xaffcaf02,0xad4dae3f,0x244e2d27,0xafddaf80,0xa9f1ae7c,0xa9f1ac32,0xaeb5aaaa,0xafe6b000,0x2d7225db,0x9cb6a6a1,0xaed0b000,0xaf02af91,0x2fa02fbc,0x28d5244e,0x230eab05,
0x2b052d00,0xa44e2b5e,0xafbcaf1a,0x2f912faf,0x16482765,0xafd4ad72,0xafddafff,0x16482cb0,0xaaaaa6a1,0xac32af5a,0xae7caf5a,0xaf80ac87,0xae1facd8,0x2d001fd9,0xabb7ad4d,0xad27afbc,
0x2f6e2e5e,0x2fd42f30,0xa6a11fd9,0x2dba244e,0x2fe62ff4,0x1cb62d27,0xad72ab5e,0x2ed02ff4,0x2e1f2f46,0xafafacb0,0xafafaed0,0xa8d52993,0x29342c87,0xac07af6e,0xafbcb000,0xaffcae99,
0xa8d5acb0,0x2875aaaa,0x2e3f2f80,0xa8d5aed0,0x29341648,0x2fed2eb5,0x28142c5d,0x2f302a4e,0x2e992cd8,0x16482d4d,0xa9f19fd9,0x2c872fbc,0x2fff2faf,0xafe6ad27,0xaed0ad27,0xaddca30e,
0xafc9ae99,0xaf80af5a,0x2f462d96,0xafe6ae99,0xaf02afed,0x28d5ab05,0x2fa02ffc,0x230eacd8,0xa934ad27,0x2fbc2f02,0x2c072e3f,0x2ffc2e1f,0x2a4e1cb6,0xa6a12c32,0xa6a12515,0x96482d72,
0xaaaa29f1,0xaed025db,0xacb025db,0x2f801648,0xaf1aaf91,0x2875ae5e,0xae3fafed,0xab5e2d4d,0x2c07a875,0x2b052ff8,0x2d4da17e,0xa814aff4,0x2eb52fc9,0xaf6ead72,0x2dba2fff,0x2eb52e7c,
0x2f022f80,0x2b5e2fe6,0x2b5e2fc9,0x230eaf46,0xacd826a1,0xaf30ad96,0xaf91a9f1,0x2c072fd4,0xad96affc,0x2fdd244e,0xa5dbaee9,0xaf5aad4d,0x2e7c217e,0xad722bb7,0x2fff2d00,0x2fc9217e,
0x2c5da934,0x2f5aa44e,0x30002cd8,0xaeb5adfe,0x2d722ff8,0xacb02d00,0xa7652d00,0x2fff28d5,0xaf02a515,0x217eaf80,0xaf1aaf46,0xaf022765,0xa814af5a,0x2b052fdd,0x2d4da5db,0x2c07ad96,
0xae5eafa0,0xa934aff4,0x2b05abb7,0xaee928d5,0x2eb51cb6,0x2d962ed0,0x2d962fe6,0x2c87ad72,0x27652f6e,0xaf80ac5d,0xaf46a5db,0xa5152f6e,0xaff4ad4d,0x2ff8244e,0xa17eaee9,0xa875affc,
0xad4d2875,0xafbc217e,0xacd8aff8,0x1fd92ff4,0xaa4eafe6,0x2e99aaaa,0x2fd42993,0xaa4eafc9,0x2fff2c87,0xacb02d96,0xa7652d96,0x2d722eb5,0xab5e2c07,0x2875af30,0xae3faf91,0xaf1aacd8,
0x2d962fbc,0x25db2ffc,0xafdda934,0x2f5a2c07,0xafc9a875,0xaaaaafa0,0x2993ad27,0xafe6a875,0x28d5ad72,0x2d002ed0,0x2d002fe6,0x2ff81cb6,0x2d4d2fd4,0xae5ead96,0xafeda9f1,0xaf9126a1,
0x2e1fa765,0x2ff49cb6,0xa8752ddc,0x2e1facb0,0x1fd92f5a,0xafbc25db,0xacd8afdd,0xad4d2d96,0xaeb5aee9,0x2f5aa934,0x30002b05,0x2c5dae5e,0x2f80230e,0xaed02b5e,0xacb02b5e,0xaaaa2f02,
0xacb0afd4,0x9cb6b000,0x2ddc2f5a,0xa765afd4,0x2ff42c07,0x217e2ffc,0xaff8a934,0x28752fbc,0xadfe28d5,0xa44eaff4,0x2cd8abb7,0xa934afa0,0x1648af46,0x25db2fe6,0x25db2fc9,0x29f12f80,
0xafff9648,0xae7ca6a1,0xafc9a6a1,0x2d722a4e,0x2ff81fd9,0x230e2ee9,0x2faf2814,0x217eaf91,0xafeda30e,0x2d4dafa0,0xaf91a8d5,0xae5e2f02,0x2fdd2515,0xb0002aaa,0x2f6e2993,0x2fdda765,
0xa30e2fff,0xad272fc9,0xad272e7c,0x2fafad72,0x2814afdd,0x2ffcaa4e,0x2dfeadba,0xae5ea5db,0xaa4e2f91,0xac5dac07,0xaeb52cd8,0x96482f30,0x2c32af1a,0xa9932ff4,0x2f46abb7,0x2e7caf1a,
0x2fdd1fd9,0x2dba2814,0x2a4e2ee9,0x25dbaf91,0xaf46a8d5,0x2765afaf,0xa515afaf,0xaf802e1f,0x2e3f2c32,0xafa02ddc,0xa17e2fff,0x2e3f2515,0xacd8adba,0x2dfe26a1,0x2934afd4,0x244eaf6e,
0x2814aff8,0x2dfeafaf,0x2ffca30e,0xae5ea17e,0xac872f46,0xaf5a2515,0xaf5aa765,0xa6a12f80,0x2e7cadba,0x1cb62e99,0x2ddc2c5d,0x2fc9adba,0xafaf2b05,0x2f1aaee9,0xab5eae5e,0xad00a934,
0xaf91a30e,0xacd8a8d5,0x2c07afa0,0xaf302f02,0x2dba2c32,0xac5d2fff,0xae992ddc,0x2dba2515,0xa993aeb5,0x2fc9a9f1,0x2fe6a9f1,0x2aaaafdd,0xa17e2fed,0xa30eadfe,0xafaf9fd9,0xaff82c07,
0xaa4e2fed,0xaeb52f91,0xac5dad4d,0x96482e5e,0x2e7cae3f,0x2ddc217e,0x1cb62fa0,0x2fc9ae3f,0xaff82993,0x2bb7afe6,0x2bb7afc9,0xab5eaaaa,0x2f3025db,0xafbc2a4e,0xaee92dba,0xadfe2fdd,
0x2f1a2515,0x2bb72993,0xaff42aaa,0x2f1aa765,0xab05adba,0x2e5eafd4,0x2ee926a1,0x2934af6e,0xa5db2fed,0xadba9fd9,0xaa4eadfe,0xafdd2c07,0x2ddcaf02,0xacb02ff8,0xa7652ff8,0x9cb62e3f,
0x2c32afdd,0x2f46af6e,0xa9933000,0x2e7cafdd,0xafaf2cd8,0xab5ea934,0x2f1aadfe,0xad00a44e,0x2f30217e,0xaee92faf,0xafbc230e,0xadfe2ff8,0xa9f1addc,0x2c5d2765,0x2c5d2cb0,0x2d961cb6,
0xa993aa4e,0x2765ac87,0xa515ac87,0xaaaa2dba,0xafa02f30,0xabb7244e,0xaff42e5e,0x28d51fd9,0x28142bb7,0xaf912e1f,0x1fd92d27,0x2ee9ad00,0x2fd4aed0,0xaf5a2fff,0x3000addc,0x2fd4afe6,
0xafaf2f46,0xafa02e7c,0xafa02c32,0x2d00a993,0x244e2c5d,0xaf913000,0xab052f5a,0x2fbcaeb5,0x3000adfe,0xac872e5e,0x2e99a814,0x2f6eaffc,0x2515ae1f,0x1cb62875,0x2d72aff4,0x2c32ae1f,
0x26a12b05,0xa9f12cd8,0xad962fed,0x2fd4affc,0x2fffae1f,0x2515230e,0x2c32230e,0x2ddcaf1a,0x2875ae7c,0x2d27aaaa,0x2fa0af80,0x2875ac32,0xaee929f1,0x2f91ae99,0x9fd9ac87,0xa8149648,
0x2fedaf1a,0x2f30ae3f,0x29342875,0x2814ab5e,0x26a1addc,0x3000afc9,0x3000ae7c,0xa5db9cb6,0xaed02a4e,0x2f46afd4,0x2993ae99,0xacb02a4e,0xae3f2ffc,0x2d27ae5e,0xae1f2814,0xaf022dfe,
0x9fd9abb7,0x2c07ad27,0x2fedae1f,0xadfe2d00,0xaf6e2cb0,0x25dba993,0x2c5daf46,0xaf6e2ed0,0xaddc2fdd,0xa5159648,0xac329648,0xafff2fd4,0x28d52814,0xabb72934,0xaff42f30,0xafa02fed,
0xb0002ee9,0xae992dfe,0x2c87af30,0xaf6e2fbc,0xac322f02,0xaf802f1a,0xaaaaa17e,0xae7c2f02,0x2b5e1cb6,0xaff42fc9,0xaff42e7c,0xad272ddc,0x2ffcaeb5,0xafed3000,0xacd82f5a,0xab052c5d,
0xa17e2c32,0xad002d72,0xabb71cb6,0xa17e2515,0x2dfea9f1,0xac072c87,0xafed2e99,0x1fd91648,0x2fd4afbc,0xa9f12b05,0xad962f91,0x26a1a44e,0x2aaaae3f,0xa76528d5,0x251528d5,0x2993a875,
0x2fe6aeb5,0x2ddcadba,0xafff2f6e,0x2ed0aeb5,0x2e3fafbc,0x2e1fadfe,0xad272f30,0x2f02aee9,0x1fd9ab5e,0x2e5eae3f,0x244e2875,0x2f30af1a,0xad962993,0x2e99ae7c,0x2e99ac32,0x2f5aaf46,
0x299329f1,0xa76525db,0x251525db,0x2aaa1648,0x28d52934,0xaf02acd8,0x230e244e,0x2fa02dfe,0x28142875,0xaf91aff8,0x1fd9217e,0x2ee92ff4,0x26a12765,0xaa4eaddc,0x16481cb6,0x26a12cb0,
0x2f022f46,0x2b5e2e7c,0x2b5e2c32,0x230ea993,0x2e5e2eb5,0xab051648,0x29342a4e,0x2ee92c5d,0x2d962dfe,0xafddae5e,0x25db2814,0x2f5a2ffc,0x2cb02d27,0xaddcafaf,0x1cb6230e,0x27652d27,
0x2fd42f91,0x2f6e2fed,0x2dba2e5e,0xa6a1ad4d,0x2fff2ff8,0x25152d00,0x2c322d00,0x2ddc28d5,0x2faf2fe6,0xae1fa993,0x28d52aaa,0x2faf2fc9,0x2ee92f5a,0xaf91afdd,0x1fd925db,0x28142d96,
0x2cd82b5e,0x2f912d00,0x2f302faf,0xac07af1a,0x2eb52ddc,0x2d962fc9,0x2d962e7c,0x2c871cb6,0x2fc92f5a,0xa99326a1,0x2aaa2c87,0x2fe62f5a,0x2ff42ffc,0xaff8ae5e,0x217e2814,0x28752dfe,
0x9fd9a875,0x2c07a17e,0x2fed2ff8,0xadfeaff4,0x29f12515,0x2fdd2f46,0x2eb52f80,0x29f1a765,0x2ddc2c87,0x25152d96,0x2c322d96,0x2fff2eb5,0x2fa02ee9,0xaf02ab05,0x230e2934,0x28d52e5e,
0xad96aee9,0xa5dbadfe,0x2fdd2f30,0xaf5aafbc,0xa765abb7,0x2f462b5e,0x2f802ff8,0x2515abb7,0x28d51cb6,0x2d002fc9,0x2d002e7c,0x2ff82ddc,0x2dfe2c5d,0xacd81648,0x244e2a4e,0x29342eb5,
0xaff8afc9,0xae3fafff,0x2f022d72,0xaff8ae7c,0xadfeaf5a,0x2c07a5db,0x2fed2fdd,0x9fd9ad96,0xa6a1ac07,0x2f6e2f91,0x2dba2f30,0x2fd42cd8,0x2aaa230e,0xa7652b5e,0x25152b5e,0x29932f02,
0xae7cac5d,0xafffad96,0x2d7229f1,0xafc9ac5d,0xaff4afbc,0xa17eadfe,0x2ff82f30,0xa875aee9,0xad4daf1a,0x2fed2d00,0x2e5e2faf,0x2f912b5e,0x1648a993,0x25db2e7c,0x25db2c32,0x29f12f46,
0xaddc9648,0xafe6a6a1,0xaed0a6a1,0x2fff2a4e,0xad27affc,0x2d00ac07,0xabb7afbc,0xae1f2934,0x2e5e230e,0x1fd92fa0,0x2f3028d5,0x244eaf02,0x2c872fe6,0xadbaaf46,0x2a4e2f80,0x2c872fc9,
0xa30e2d72,0xad272c32,0xad272515,0x2faf1cb6,0xafbcae99,0x1fd9af6e,0xad4db000,0xacd82c87,0x2a4eab05,0x2c5d2fbc,0x2eb5244e,0x1648af91,0x2ed02fa0,0xaf80ad00,0x2aaa2faf,0x2cb02fa0,
0x2c872ffc,0x16482fbc,0xa9f12c07,0x2e99a934,0xaf80a8d5,0xac32afaf,0xae7cafaf,0xaaaa2e1f,0xa30eaed0,0x2f1a2d72,0x2e1f9cb6,0xa30eafe6,0x2fed2dba,0xaffca6a1,0x2b052fd4,0x2cd82f6e,
0x2fbc2e1f,0x2d4d2f02,0x9fd92e3f,0x2cd8ad27,0xac872993,0xaf5aacb0,0xaf5aaed0,0xa6a12f46,0xacb0b000,0x2fff25db,0x2d72a6a1,0xa765b000,0x2faf2934,0xaf1a2814,0x2b5e2fed,0x2d002f30,
0x2f30230e,0x2fed28d5,0x28142fa0,0x2934af02,0x16482ed0,0xafd41cb6,0xafddad72,0x16482fe6,0xaf46aeb5,0x2ed0a9f1,0x2cb0a9f1,0xa993afdd,0x2e1fa44e,0xad002d4d,0x2bb72ffc,0x2d272ee9,
0x2a4eacd8,0x2eb5ab05,0x2c5d2ffc,0x1648afed,0x2cb02ff4,0xad722d27,0xafffab5e,0x27652ff4,0xaff8aaaa,0x2bb7ae7c,0x2bb7ac32,0xab5eaf80,0x2b05ac87,0xa8142f6e,0x2c073000,0x2d4d2e99,
0xa8d5afe6,0x2875af80,0x2e3f2f46,0xa8d5afc9,0x2f912dba,0xa44e2fd4,0xafbca6a1,0x2b052f6e,0xae99244e,0x9648affc,0x29f1ad4d,0xac87aee9,0x1cb6af02,0x25152ff8,0x2c322ff8,0x2d722e3f,
0xaed0ae99,0xaaaaaf5a,0x2f802d96,0xacb0ae99,0x2faf244e,0x2b5e2f30,0xaf1a1fd9,0x2d002e5e,0xab052d27,0xac07af02,0x2814ae3f,0xad4dae1f,0xa9f1afff,0x2c5d2ed0,0x2c5d2fe6,0x2d962ddc,
0xaf46aa4e,0xac32ac87,0xae7cac87,0x29932dba,0x2f1a2b05,0xa8752fed,0x2e3f2cd8,0x2b5eaffc,0xaee9abb7,0x2f30ae1f,0xadfead27,0xafbc2d00,0x2eb52c32,0xaf6e1cb6,0x2dba2d72,0x2eb52515,
0xafaf2993,0xafa02515,0xafa0a765,0x2d002aaa,0x2feda6a1,0x29342d96,0x2f3029f1,0x2814afd4,0xb0001fd9,0x2c87afed,0xae99ac07,0xaf6e2dfe,0x2fe6217e,0xafff2bb7,0x2ddc2d00,0x2ed0217e,
0xac5d2f30,0xaf5a2e5e,0xb000244e,0x2eb51fd9,0x2ddcae1f,0x2e7c230e,0x2fc9230e,0x1cb6af1a,0xaf022cb0,0x217eaf46,0xaf1aa993,0xaf022ed0,0x2fbca9f1,0xaf302e99,0x2dfe2c87,0x2ee91648,
0x244e2fa0,0xab052ff4,0xaf912bb7,0x2fbca8d5,0x26a1afff,0x3000ac32,0x3000a515,0xa5dbaddc,0xac322f6e,0xaaaaac5d,0xaf80a5db,0xae7c2f6e,0x2e3fadfe,0xad272fed,0x2e1f2c07,0x2f029fd9,
0x2dfe2bb7,0x28142d27,0xae5e2e1f,0x2ffcad00,0xaa4eae7c,0x2e99af80,0x2fd4aaaa,0xaa4eac32,0x9cb62fdd,0xae7c9648,0xafc99648,0xaddc2fd4,0x2b5eafbc,0xa8752f91,0x2e3f2b05,0x2f1aa44e,
0x3000a814,0x2e999fd9,0xac872f91,0x2f6eaee9,0xaed0a875,0x2993afa0,0x2f46ad27,0xacb0a875,0x2b5e2ddc,0xaff42c32,0xaff42515,0xad272fff,0x1fd9afd4,0x244e2d96,0x2e5e29f1,0x2f30a6a1,
0x2e1faed0,0x2ff4addc,0xa8752fff,0x2e1fafe6,0xaffc29f1,0xa814ac87,0x2e5eae99,0xadfe9648,0x2eb52814,0xaf5a2f30,0xb0002934,0xac5d2fed,0xa993ae3f,0x2c3228d5,0x2e7c28d5,0x2f46a875,
0x2515afd4,0x2d72b000,0x1cb62f5a,0x2c32afd4,0xae3f2ee9,0xae1f1fd9,0x2d27af91,0xaf022814,0x2ffca8d5,0xacd82ff4,0xafed2bb7,0xab052fa0,0xad96aaaa,0x2e99a515,0x2e992765,0x2f5aa993,
0x1cb6adba,0x2cb0aeb5,0x2765aeb5,0xaddc2f6e,0xaff82d4d,0xa30ea814,0xafaf2c07,0xa17e2b05,0xa44e2e3f,0xadfe2b5e,0xa9342f1a,0x2cd8a875,0x2fddacb0,0xb0002f80,0x2f6eaaaa,0x2fddaed0,
0xad009cb6,0xa17ea765,0xa17eacb0,0xabb72ddc,0xaee92fdd,0xad4d2a4e,0xaffc2dba,0x244e25db,0x29f12934,0xafd42ee9,0xa6a12e5e,0x2d96ab05,0x2fc9af1a,0xaf462ff4,0x2f80abb7,0x2fe6af1a,
0xafdd2d4d,0xadba2c07,0xaa4ea814,0xa5db2b05,0xaaaa2f1a,0xafc92f02,0xafe62f02,0x2993a17e,0x2e3fa765,0xafa02fff,0xa17e2d72,0x2e3facb0,0x2e5eb000,0xad4d2eb5,0x2f91ac5d,0x2fedaf5a,
0xaee92ff8,0xaffc2faf,0xad4d230e,0x244e217e,0x25db2aaa,0xaf6e2fe6,0xaf6e2fc9,0x2c5da993,0x2fe6adba,0xad722e99,0x1cb62c5d,0x2ed0adba,0x2bb7af30,0xa8d52c07,0x2fa0acd8,0x2ff4af91,
0xa9342e3f,0xae5e2f1a,0xaee92b5e,0x2b05a875,0x2dbaa765,0xac5d2d72,0xae992fff,0x2dbaacb0,0x2f80afd4,0xa7652a4e,0x25152a4e,0x2f46ae99,0x217eacd8,0x230e1fd9,0x2fafad4d,0x2ff8afbc,
0x29f1244e,0xa6a12934,0xafd42dfe,0x2d96acd8,0x2fe6ae3f,0x1cb6217e,0xad722fa0,0x2ed0ae3f,0x2d27af80,0x2875a515,0x28752765,0x2fa0af46,0xa934a5db,0x2c07aa4e,0x2fbcadba,0x2ffcafdd,
0x2f1aacb0,0x2bb7aaaa,0xaff42f80,0x2f1aaed0,0x2f30b000,0x2cd8ac5d,0xac072eb5,0x2f91af5a,0x25dbacd8,0x2dbaad4d,0x2a4e1fd9,0x2fddafbc,0xad722875,0x2e7cae1f,0x2fc9ae1f,0x2fffaff4,
0x2fc9afdd,0x2f80af6e,0xaf463000,0x2fe6afdd,0x2bb7ae5e,0x2fa0af91,0xa8d52d4d,0x2ff4afed,0xa934a17e,0x2fbcafaf,0x2c07a30e,0x2ffcaff8,0xaf5a2d72,0x2fd4afc9,0x2fd4ae7c,0x3000afff,
0x3c003c00,0x3bff3c00,0x3c003c00,0x3bfa3bfd,0x3c003c00,0x3bef3bf5,0x3c003c00,0x3bde3be7,0x3c003c00,0x3bc83bd4,0x3c003c00,0x3bac3bbb,0x3c003c00,0x3b8b3b9d,0x3bff3c00,0x3b653b79,
0x3c003c00,0x3bff3c00,0x3c003c00,0x3bf83bfd,0x3bff3c00,0x3bea3bf2,0x3bff3bff,0x3bd63be1,0x3bfe3bff,0x3bba3bc9,0x3bfd3bfe,0x3b983baa,0x3bfc3bfd,0x3b6f3b84,0x3bfb3bfc,0x3b3f3b58,
0x3c003c00,0x3bff3c00,0x3bff3c00,0x3bf63bfc,0x3bfe3bff,0x3be53bef,0x3bfd3bfe,0x3bcc3bda,0x3bfb3bfc,0x3bab3bbc,0x3bf93bfa,0x3b813b97,0x3bf63bf7,0x3b4f3b69,0x3bf23bf4,0x3b163b33,
0x3c003c00,0x3bff3c00,0x3bff3c00,0x3bf53bfb,0x3bfd3bfe,0x3be03bec,0x3bfa3bfc,0x3bc23bd2,0x3bf63bf8,0x3b9a3baf,0x3bf23bf4,0x3b683b82,0x3bec3bef,0x3b2c3b4b,0x3be53be9,0x3ae83b0b,
0x3c003c00,0x3bfe3c00,0x3bfe3bff,0x3bf23bfa,0x3bfb3bfd,0x3bda3be8,0x3bf63bf9,0x3bb73bca,0x3bf03bf4,0x3b873ba0,0x3be83bed,0x3b4c3b6b,0x3bdf3be4,0x3b073b2b,0x3bd43bda,0x3ab63ae0,
0x3c003c00,0x3bfe3c00,0x3bfd3bff,0x3bf03bf9,0x3bf93bfb,0x3bd43be4,0x3bf23bf6,0x3bab3bc1,0x3be83bed,0x3b733b91,0x3bdd3be3,0x3b2f3b53,0x3bcf3bd6,0x3ade3b08,0x3bbf3bc7,0x3a813ab1,
0x3c003c00,0x3bfe3c00,0x3bfc3bfe,0x3bee3bf8,0x3bf63bf9,0x3bce3be0,0x3bec3bf1,0x3b9e3bb7,0x3bdf3be6,0x3b5e3b80,0x3bcf3bd7,0x3b103b39,0x3bbc3bc6,0x3ab33ae3,0x3ba53bb1,0x3a493a7f,
0x3bff3c00,0x3bfe3c00,0x3bfb3bfe,0x3beb3bf7,0x3bf23bf7,0x3bc63bdb,0x3be53bed,0x3b903bad,0x3bd43bdd,0x3b473b6e,0x3bbf3bca,0x3aee3b1d,0x3ba53bb2,0x3a853abc,0x3b873b97,0x3a0d3a4b,
0x3bfd3c00,0x3bfa3c00,0x3be83bf6,0x3bcc3be9,0x3bbf3bd6,0x3b713ba4,0x3b813ba2,0x3aeb3b33,0x3b2f3b5a,0x3a3d3a99,0x3acb3aff,0x396b39d8,0x3a543a92,0x387a38f6,0x39cd3a13,0x36dd37ee,
0x3bfd3c00,0x3bfa3c00,0x3be53bf4,0x3bc83be7,0x3bb73bd1,0x3b653b9d,0x3b713b97,0x3ad53b22,0x3b163b46,0x3a193a7c,0x3aa53ae0,0x393739ad,0x3a213a65,0x383538ba,0x398b39d8,0x36313753,
0x3bfd3c00,0x3bf93c00,0x3be23bf3,0x3bc33be5,0x3bae3bcb,0x3b593b95,0x3b603b8a,0x3abd3b11,0x3afb3b30,0x39f43a5e,0x3a7e3abf,0x39023980,0x39eb3a37,0x37dd387c,0x3946399b,0x358136b5,
0x3bfc3c00,0x3bf93c00,0x3bdf3bf1,0x3bbf3be3,0x3ba53bc6,0x3b4c3b8c,0x3b4f3b7d,0x3aa53aff,0x3ade3b1a,0x39cd3a3f,0x3a543a9c,0x38cc3951,0x39b33a07,0x374e383d,0x38fd395b,0x34cf3614,
0x3bfc3c00,0x3bf83c00,0x3bdc3bf0,0x3bba3be1,0x3b9c3bc0,0x3b3f3b84,0x3b3d3b70,0x3a8c3aed,0x3ac13b02,0x39a63a1f,0x3a293a78,0x38943922,0x397939d4,0x36bb37f9,0x38b23918,0x341a3570,
0x3bfc3c00,0x3bf83c00,0x3bd83bee,0x3bb53bdf,0x3b923bb9,0x3b323b7b,0x3b2a3b62,0x3a733ad9,0x3aa23ae9,0x397d39fe,0x39fc3a52,0x385a38f1,0x393c399f,0x36253775,0x386538d3,0x32c634c9,
0x3bfb3c00,0x3bf73c00,0x3bd43bed,0x3bb03bdc,0x3b873bb2,0x3b243b72,0x3b163b53,0x3a583ac6,0x3a813ad0,0x395439dc,0x39cd3a2b,0x382038bf,0x38fd3969,0x358d36ee,0x3815388c,0x31533420,
0x3bfb3c00,0x3bf63c00,0x3bd03beb,0x3bab3bda,0x3b7c3bab,0x3b163b69,0x3b013b43,0x3a3d3ab1,0x3a603ab5,0x392939ba,0x399d3a02,0x37c8388c,0x38bc3930,0x34f33665,0x37853842,0x2fbd32ea,
0x3bf63c00,0x3bf03c00,0x3ba53bd7,0x3b733bc1,0x3b073b5f,0x3a813b08,0x3a213a9c,0x392939e1,0x38fd3996,0x36ff385d,0x374e3858,0x327c3529,0x345735da,0xa9b12d1a,0x2cce3191,0xb49fb160,
0x3bf53c00,0x3bef3c00,0x3b9f3bd5,0x3b6c3bbe,0x3af73b55,0x3a6f3afc,0x3a043a87,0x390739c7,0x38d13972,0x36993832,0x36d23822,0x316c34b1,0x3371354c,0xad65297f,0x27763036,0xb552b2b9,
0x3bf53c00,0x3bef3c00,0x3b9a3bd2,0x3b653bbb,0x3ae83b4b,0x3a5c3af0,0x39e73a71,0x38e539ad,0x38a3394d,0x36313807,0x365437d8,0x305b3438,0x323234bd,0xafef1e48,0xa4522db0,0xb602b408,
0x3bf43c00,0x3bee3c00,0x3b943bd0,0x3b5e3bb7,0x3ad83b41,0x3a493ae3,0x39c93a5a,0x38c13992,0x38743927,0x35c837b7,0x35d4376a,0x2e91337d,0x30f0342c,0xb13ba7da,0xac0629e3,0xb6afb4b1,
0x3bf33c00,0x3bed3c00,0x3b8e3bcd,0x3b573bb4,0x3ac73b36,0x3a353ad6,0x39aa3a43,0x389e3976,0x38453900,0x355e375e,0x355236f9,0x2c6a3288,0x2f593334,0xb27cac51,0xaef51a48,0xb759b558,
0x3bf23c00,0x3bec3c00,0x3b873bca,0x3b4f3bb1,0x3ab63b2b,0x3a213ac9,0x398b3a2b,0x387a395b,0x381538d8,0x34f33705,0x34cf3687,0x28843191,0x2cce320d,0xb3baaeaa,0xb0f0a91b,0xb7feb5fd,
0x3bf23c00,0x3beb3c00,0x3b813bc7,0x3b473bad,0x3aa53b20,0x3a0d3abc,0x396b3a13,0x3855393e,0x37c838b0,0x348736aa,0x344b3614,0x16483099,0x288430e4,0xb47bb080,0xb263ad4c,0xb850b69e,
0x3bf13c00,0x3bea3c00,0x3b7a3bc4,0x3b3f3baa,0x3a933b14,0x39f83aae,0x394a39fa,0x38303922,0x37643887,0x341a364e,0x3389359f,0xa81f2f40,0x9cb62f72,0xb517b1aa,0xb3d3b004,0xb89eb73d,
0x3be93c00,0x3be13c00,0x3b373ba6,0x3af13b86,0x39e33aa0,0x392e3a27,0x380a3905,0x3599380d,0x335935f1,0x217f31db,0xac382d4c,0xb546b12e,0xb5b1b2d2,0xb90cb7cd,0xb8eab7d8,0xbadbba0b,
0x3be83c00,0x3be03c00,0x3b2f3ba2,0x3ae83b82,0x39cd3a92,0x39163a17,0x37c838e7,0x354637d8,0x327c3593,0xa4523115,0xae5f2aac,0xb5c8b226,0xb648b3f7,0xb94ab828,0xb933b838,0xbb0aba43,
0x3be73c00,0x3bdf3c00,0x3b273b9e,0x3ade3b7d,0x39b83a83,0x38fd3a07,0x377a38c9,0x34f33796,0x319e3534,0xa9b1304e,0xb042257f,0xb648b31b,0xb6ddb48d,0xb986b867,0xb979b881,0xbb35ba78,
0x3be63c00,0x3bde3c00,0x3b1e3b9b,0x3ad53b79,0x39a13a74,0x38e539f6,0x372c38ab,0x349f3753,0x30be34d5,0xac9c2f0e,0xb153a0b6,0xb6c6b408,0xb76fb51d,0xb9c0b8a6,0xb9bcb8c9,0xbb5cbaaa,
0x3be53c00,0x3bdd3c00,0x3b163b97,0x3acb3b74,0x398b3a65,0x38cc39e5,0x36dd388c,0x344b3710,0x2fbd3475,0xae5f2d7e,0xb263a91b,0xb742b481,0xb7feb5ab,0xb9f8b8e2,0xb9fcb90e,0xbb7fbad9,
0x3be43c00,0x3bdc3c00,0x3b0d3b93,0x3ac13b70,0x39743a56,0x38b239d4,0x368d386d,0x33eb36cc,0x2dfb3414,0xb0102bd9,0xb371ac83,0xb7bdb4f9,0xb845b637,0xba2db91d,0xba39b951,0xbb9ebb05,
0x3be33c00,0x3bda3c00,0x3b043b8f,0x3ab63b6b,0x395d3a47,0x389939c3,0x363c384d,0x33403687,0x2c383365,0xb0f028b6,0xb43eae78,0xb81ab570,0xb889b6c1,0xba60b956,0xba73b992,0xbbb8bb2e,
0x3be23c00,0x3bd93c00,0x3afb3b8a,0x3aac3b67,0x39463a37,0x387f39b1,0x35eb382d,0x32943642,0x28e832a1,0xb1cf2248,0xb4c3b036,0xb855b5e5,0xb8ccb748,0xba90b98d,0xbaa9b9d0,0xbbcfbb53,
0x3c003c00,0x3bfe3c00,0x3c003c00,0x3bf73bfc,0x3c003c00,0x3beb3bf2,0x3c003c00,0x3bd93be3,0x3c003c00,0x3bc13bce,0x3c003c00,0x3ba53bb4,0x3c003c00,0x3b823b94,0x3bff3bff,0x3b5b3b6f,
0x3c003c00,0x3bfe3c00,0x3c003c00,0x3bf53bfb,0x3bff3c00,0x3be63bee,0x3bff3bff,0x3bcf3bdb,0x3bfe3bfe,0x3bb23bc1,0x3bfd3bfe,0x3b8e3ba1,0x3bfc3bfd,0x3b643b7a,0x3bfb3bfb,0x3b333b4c,
0x3c003c00,0x3bfe3c00,0x3bff3c00,0x3bf33bf9,0x3bfe3bff,0x3be03beb,0x3bfd3bfd,0x3bc53bd3,0x3bfb3bfc,0x3ba13bb4,0x3bf83bf9,0x3b753b8c,0x3bf53bf7,0x3b413b5c,0x3bf23bf3,0x3b063b25,
0x3c003c00,0x3bfd3c00,0x3bff3bff,0x3bf03bf8,0x3bfc3bfe,0x3bda3be6,0x3bf93bfb,0x3bb93bca,0x3bf53bf7,0x3b8e3ba5,0x3bf03bf3,0x3b5a3b75,0x3beb3bee,0x3b1c3b3c,0x3be43be7,0x3ad53afa,
0x3c003c00,0x3bfd3c00,0x3bfe3bff,0x3bee3bf7,0x3bfa3bfc,0x3bd33be2,0x3bf53bf8,0x3bac3bc1,0x3bee3bf2,0x3b7a3b94,0x3be63beb,0x3b3c3b5c,0x3bdd3be2,0x3af43b19,0x3bd13bd7,0x3aa13acb,
0x3bff3c00,0x3bfc3c00,0x3bfc3bfe,0x3beb3bf5,0x3bf73bfa,0x3bcb3bdd,0x3bf03bf4,0x3b9e3bb6,0x3be63beb,0x3b643b82,0x3bda3be0,0x3b1c3b41,0x3bcb3bd3,0x3ac83af4,0x3bba3bc3,0x3a683a9a,
0x3bff3c00,0x3bfb3bff,0x3bfb3bfd,0x3be73bf3,0x3bf43bf8,0x3bc33bd7,0x3be93bef,0x3b8f3bab,0x3bdb3be3,0x3b4c3b6f,0x3bca3bd3,0x3afa3b25,0x3bb63bc1,0x3a9a3acb,0x3b9f3bab,0x3a2c3a65,
0x3bff3c00,0x3bfb3bff,0x3bf93bfd,0x3be43bf2,0x3bf03bf5,0x3bba3bd1,0x3be23be9,0x3b7f3b9f,0x3bcf3bd9,0x3b333b5b,0x3bb93bc5,0x3ad53b06,0x3b9e3bac,0x3a683aa1,0x3b7f3b8f,0x39ec3a2c,
0x3bfa3bff,0x3bf33bff,0x3be03bf0,0x3bba3bdc,0x3bb13bcb,0x3b533b8c,0x3b6e3b92,0x3ac33b10,0x3b183b45,0x3a0c3a6c,0x3aaf3ae5,0x393139a3,0x3a343a73,0x383938b9,0x39a939f1,0x36513767,
0x3bf93bff,0x3bf23bfe,0x3bdc3bee,0x3bb43bd9,0x3ba73bc5,0x3b453b82,0x3b5c3b85,0x3aa93afd,0x3afb3b2e,0x39e43a4c,0x3a863ac3,0x38fa3973,0x39fd3a44,0x37e03878,0x396339b2,0x359c36c3,
0x3bf93bff,0x3bf13bfe,0x3bd83beb,0x3bae3bd6,0x3b9d3bbe,0x3b373b78,0x3b493b76,0x3a8f3ae9,0x3add3b16,0x39bb3a2a,0x3a5b3a9f,0x38c03942,0x39c43a12,0x374b3836,0x39193971,0x34e4361d,
0x3bf83bff,0x3bf03bfe,0x3bd33be9,0x3ba73bd3,0x3b923bb6,0x3b273b6e,0x3b353b67,0x3a733ad4,0x3abe3afd,0x39913a08,0x3a2e3a79,0x38853910,0x398839de,0x36b237e6,0x38cd392d,0x34293573,
0x3bf73bff,0x3bee3bfe,0x3bcf3be7,0x3ba13bcf,0x3b873baf,0x3b183b64,0x3b203b57,0x3a573abe,0x3a9d3ae2,0x396539e4,0x39ff3a51,0x384938dc,0x394939a7,0x3617375c,0x387e38e6,0x32d834c6,
0x3bf63bff,0x3bed3bfe,0x3bca3be4,0x3b9a3bcc,0x3b7b3ba6,0x3b073b58,0x3b0a3b47,0x3a3a3aa8,0x3a7b3ac6,0x393939bf,0x39cf3a28,0x380b38a7,0x3908396e,0x357936cf,0x382c389d,0x315a3417,
0x3bf53bff,0x3bec3bfe,0x3bc53be2,0x3b933bc8,0x3b6e3b9e,0x3af73b4d,0x3af43b35,0x3a1c3a91,0x3a573aa9,0x390b399a,0x399c39fd,0x37993871,0x38c53934,0x34d8363f,0x37af3851,0x2fb032cc,
0x3bf43bff,0x3beb3bfe,0x3bbf3bdf,0x3b8c3bc5,0x3b613b95,0x3ae53b41,0x3adc3b23,0x39fd3a79,0x3a323a8b,0x38dc3973,0x396739d1,0x37183839,0x388038f7,0x343535ae,0x37023803,0x2ca93166,
0x3be93bfd,0x3bdd3bfc,0x3b853bc1,0x3b413b9e,0x3ad43b35,0x3a343ac8,0x39de3a61,0x38c53988,0x38ac394b,0x361737e0,0x36963800,0x30863435,0x3322351a,0xaecf2484,0x267b2ffb,0xb590b352,
0x3be83bfd,0x3bdb3bfc,0x3b7d3bbd,0x3b383b99,0x3ac13b29,0x3a1e3ab9,0x39bd3a48,0x389f396a,0x387b3923,0x35a83783,0x3611378e,0x2ecf336b,0x31d53484,0xb0b8a54d,0xa5b22d26,0xb645b45a,
0x3be63bfd,0x3bd93bfc,0x3b753bb9,0x3b2e3b94,0x3aaf3b1c,0x3a083aa9,0x399c3a2e,0x3878394b,0x384938fa,0x35373724,0x358a3718,0x2c903269,0x308633d9,0xb207ab8e,0xac77289d,0xb6f6b508,
0x3be53bfd,0x3bd73bfb,0x3b6d3bb5,0x3b253b8f,0x3a9b3b0f,0x39f13a9a,0x397a3a14,0x3851392d,0x381638cf,0x34c636c3,0x350236a1,0x289d3166,0x2e6b32a7,0xb352ae39,0xaf7ea052,0xb7a4b5b3,
0x3be33bfd,0x3bd53bfb,0x3b653bb0,0x3b1b3b8a,0x3a883b01,0x39d93a8a,0x395739f9,0x3829390d,0x37c538a4,0x34543662,0x34783628,0x12483061,0x2b8e3172,0xb44eb055,0xb141aac5,0xb826b65c,
0x3be23bfd,0x3bd33bfb,0x3b5c3bac,0x3b103b85,0x3a733af4,0x39c13a79,0x393439de,0x380038ed,0x375c3878,0x33c035ff,0x33d935ae,0xa86b2eb6,0x2484303c,0xb4f0b18b,0xb2bfae39,0xb878b702,
0x3be03bfc,0x3bd13bfb,0x3b533ba7,0x3b063b7f,0x3a5f3ae5,0x39a93a68,0x391039c1,0x37af38cd,0x36f1384c,0x32d8359c,0x32bf3531,0xac772ca9,0xa6162e07,0xb590b2bf,0xb41db086,0xb8c8b7a4,
0x3bde3bfc,0x3bcf3bfb,0x3b4b3ba3,0x3afb3b7a,0x3a4a3ad7,0x39913a57,0x38eb39a5,0x375c38ac,0x3684381e,0x31ee3537,0x31a434b4,0xaeb62934,0xac2b2b2a,0xb62eb3f1,0xb4d8b1ee,0xb914b821,
0x3bcd3bfa,0x3bbb3bf8,0x3af03b74,0x3a933b43,0x39783a46,0x38a239b0,0x3707388b,0x344736e0,0x310334d2,0xacdb2e39,0xb07a2052,0xb690b3e5,0xb6c9b490,0xb991b87e,0xb95eb86e,0xbb30ba79,
0x3bcb3bfa,0x3bb93bf8,0x3ae53b6e,0x3a863b3c,0x395e3a34,0x3885399c,0x36b23869,0x33d93696,0x3016346c,0xaeb62c90,0xb197a616,0xb713b472,0xb761b526,0xb9ccb8be,0xb9a5b8b9,0xbb58baad,
0x3bc93bfa,0x3bb63bf8,0x3ada3b68,0x3a793b35,0x39443a22,0x38693988,0x365c3846,0x3322364b,0x2e523405,0xb04829ca,0xb2b3ab2a,0xb793b4f0,0xb7f6b5b9,0xba05b8fc,0xb9e8b901,0xbb7dbadd,
0x3bc73bfa,0x3bb43bf7,0x3acf3b62,0x3a6c3b2e,0x392a3a10,0x384c3973,0x36053824,0x326935ff,0x2c77333a,0xb13424e9,0xb3cdada3,0xb809b56d,0xb844b64b,0xba3cb939,0xba28b947,0xbb9dbb0a,
0x3bc53bf9,0x3bb13bf7,0x3ac33b5c,0x3a5f3b27,0x391039fd,0x382e395e,0x35ae3800,0x31b035b3,0x29343269,0xb21f9f12,0xb472afb0,0xb846b5e8,0xb88bb6da,0xba70b973,0xba65b98a,0xbbb9bb34,
0x3bc23bf9,0x3baf3bf7,0x3ab73b56,0x3a513b20,0x38f539ea,0x38113949,0x355537ba,0x30f63567,0x21e43197,0xb309a839,0xb4fcb0de,0xb883b662,0xb8cfb767,0xbaa1b9ab,0xba9db9ca,0xbbd0bb5a,
0x3bc03bf9,0x3bac3bf7,0x3aab3b50,0x3a443b19,0x38d939d7,0x37e63934,0x34fc3772,0x303c351a,0xa48430c5,0xb3f1ab8e,0xb584b1e2,0xb8beb6da,0xb912b7f1,0xbacfb9e2,0xbad2ba08,0xbbe3bb7c,
0x3bbe3bf9,0x3ba93bf6,0x3a9f3b49,0x3a363b12,0x38be39c4,0x37a9391e,0x34a23729,0x2f0134cc,0xa9fd2fe2,0xb46cad71,0xb60bb2e4,0xb8f7b750,0xb953b83c,0xbafaba16,0xbb03ba42,0xbbf1bb9a,
0x96488000,0xa6ad8000,0x9cb69a48,0xad00aaac,0x9fdb9e48,0xb029aeaa,0xa17fa0b6,0xb1cfb0fd,0xa311a248,0xb371b2a1,0xa452a3db,0xb487b420,0xa51ba4b6,0xb552b4ed,0xa5e4a57f,0xb61ab5b6,
0x9cb68000,0xa7768000,0xa311a0b6,0xad97ab75,0xa5e4a4b6,0xb0a6af72,0xa81fa711,0xb27cb191,0xa94da8b6,0xb426b365,0xaa7aa9e3,0xb50bb499,0xaba7ab11,0xb5ebb57c,0xac6aac1f,0xb6c6b659,
0x9fdb8000,0xa81f8000,0xa5e4a3db,0xae2dac1f,0xa8e8a7da,0xb122b01d,0xaadea9e3,0xb328b226,0xac6aabd9,0xb493b414,0xad65ace7,0xb58db511,0xae5fade2,0xb682b608,0xaf59aedc,0xb76fb6f9,
0xa17f8000,0xa8848000,0xa81fa57f,0xaec3ac83,0xaadea97f,0xb19eb080,0xacceac1f,0xb3d3b2b9,0xae2dad7e,0xb4ffb475,0xaf8baedc,0xb60eb587,0xb074b01d,0xb715b693,0xb122b0cb,0xb80ab796,
0xa3118000,0xa8e88000,0xa94da711,0xaf59ace7,0xac6aab11,0xb219b0e4,0xae2dad4c,0xb43eb34c,0xafefaf0e,0xb56ab4d5,0xb0d7b067,0xb68db5fd,0xb1b6b147,0xb7a6b71b,0xb294b226,0xb85ab817,
0xa4528000,0xa94d8000,0xaa7aa852,0xafefad4c,0xad65ac51,0xb294b147,0xaf8bae78,0xb493b3df,0xb0d7b04e,0xb5d4b534,0xb1e8b160,0xb70ab670,0xb2f7b26f,0xb81ab7a1,0xb402b37d,0xb8a8b862,
0xa51b8000,0xa9b18000,0xaba7a91b,0xb042adb0,0xae5fad1a,0xb30fb1aa,0xb074afa4,0xb4e7b438,0xb1b6b115,0xb63cb593,0xb2f7b257,0xb785b6e3,0xb41ab396,0xb85fb812,0xb4b7b469,0xb8f3b8ab,
0xa5e48000,0xaa168000,0xac6aa9e3,0xb08dae14,0xaf59ade2,0xb389b20d,0xb122b067,0xb53ab481,0xb294b1db,0xb6a4b5f1,0xb402b34c,0xb7feb753,0xb4b7b45d,0xb8a3b852,0xb56ab511,0xb93cb8f1,
0xaa7a8000,0xacce8000,0xb0d7ae78,0xb328b0cb,0xb402b26f,0xb5dfb4bd,0xb58db4c9,0xb805b6f9,0xb70ab64e,0xb902b887,0xb83ab7c2,0xb9e3b976,0xb8e5b891,0xbaa2ba47,0xb982b935,0xbb3abaf3,
0xaade8000,0xad008000,0xb122aedc,0xb371b0fd,0xb43eb2d2,0xb61ab4ed,0xb5dfb511,0xb82ab73d,0xb76fb6aa,0xb92eb8b0,0xb874b817,0xba11b9a4,0xb924b8ce,0xbaceba74,0xb9c5b976,0xbb60bb1d,
0xab438000,0xad338000,0xb16caf40,0xb3bab12e,0xb47bb334,0xb654b51d,0xb631b558,0xb850b780,0xb7d2b705,0xb958b8d8,0xb8adb84d,0xba3db9d0,0xb962b909,0xbaf7baa0,0xba04b9b5,0xbb83bb43,
0xaba78000,0xad658000,0xb1b6afa4,0xb402b160,0xb4b7b396,0xb68db54c,0xb682b59f,0xb874b7c2,0xb81ab75e,0xb982b900,0xb8e5b881,0xba67b9fa,0xb99db943,0xbb1ebac9,0xba41b9f2,0xbba1bb67,
0xac068000,0xad978000,0xb201b004,0xb426b191,0xb4f3b3f7,0xb6c6b57c,0xb6d2b5e5,0xb899b802,0xb84ab7b7,0xb9aab927,0xb91bb8b5,0xba90ba23,0xb9d6b97b,0xbb42baf0,0xba7aba2b,0xbbbcbb86,
0xac388000,0xadc98000,0xb24bb036,0xb44bb1c3,0xb52fb42c,0xb6ffb5ab,0xb721b62b,0xb8bcb822,0xb87ab807,0xb9d2b94d,0xb94fb8e7,0xbab6ba4b,0xba0db9b1,0xbb63bb14,0xbab0ba62,0xbbd2bba2,
0xac6a8000,0xadfb8000,0xb294b067,0xb46fb1f4,0xb56ab45d,0xb737b5da,0xb76fb670,0xb8e0b842,0xb8a8b832,0xb9f8b972,0xb982b918,0xbadbba71,0xba41b9e5,0xbb81bb36,0xbae1ba95,0xbbe3bbbb,
0xac9c8000,0xae2d8000,0xb2deb099,0xb493b226,0xb5a5b48d,0xb76fb608,0xb7bdb6b5,0xb902b862,0xb8d6b85d,0xba1db996,0xb9b3b948,0xbafeba95,0xba73ba17,0xbb9cbb55,0xbb10bac6,0xbbf1bbd0,
0xae5f8000,0xafef8000,0xb4b7b257,0xb5d4b3df,0xb7a6b637,0xb8a8b7a1,0xb924b881,0xba1db96d,0xba41b9ba,0xbb32bab5,0xbb1ebab8,0xbbd6bb93,0xbbb3bb72,0xbbfebbf9,0xbbfabbe1,0xbba9bbe3,
0xae918000,0xb0108000,0xb4dbb288,0xb5f7b408,0xb7ddb665,0xb8c1b7cd,0xb946b8a0,0xba39b989,0xba64b9dc,0xbb4abad0,0xbb3dbad9,0xbbe2bba6,0xbbc8bb8c,0xbbf9bbfe,0xbbffbbee,0xbb8bbbd2,
0xaec38000,0xb0298000,0xb4ffb2b9,0xb61ab420,0xb80ab693,0xb8dbb7f9,0xb966b8bf,0xba54b9a4,0xba85b9fe,0xbb60bae9,0xbb59baf9,0xbbedbbb7,0xbbd9bba4,0xbbf0bc00,0xbc00bbf8,0xbb6abbbe,
0xaef58000,0xb0428000,0xb523b2ea,0xb63cb438,0xb825b6c1,0xb8f3b812,0xb986b8dd,0xba6fb9be,0xbaa5ba1f,0xbb76bb02,0xbb73bb17,0xbbf5bbc7,0xbbe7bbb9,0xbbe4bbff,0xbbfcbbfe,0xbb45bba6,
0xaf278000,0xb05b8000,0xb546b31b,0xb65fb451,0xb840b6ee,0xb90cb828,0xb9a6b8fb,0xba89b9d8,0xbac4ba3f,0xbb89bb1a,0xbb8bbb33,0xbbfbbbd5,0xbbf2bbcb,0xbbd6bbfb,0xbbf4bc00,0xbb1bbb8a,
0xaf598000,0xb0748000,0xb56ab34c,0xb682b469,0xb85ab71b,0xb924b83d,0xb9c5b918,0xbaa2b9f2,0xbae1ba5e,0xbb9cbb30,0xbba1bb4e,0xbbffbbe1,0xbbfabbdb,0xbbc3bbf5,0xbbe7bbfe,0xbaeebb6b,
0xaf8b8000,0xb08d8000,0xb58db37d,0xb6a4b481,0xb874b748,0xb93cb852,0xb9e3b935,0xbababa0b,0xbafeba7c,0xbbacbb46,0xbbb5bb67,0xbc00bbeb,0xbbffbbe8,0xbbaebbec,0xbbd7bbf9,0xbabdbb49,
0xafbd8000,0xb0a68000,0xb5b1b3ae,0xb6c6b499,0xb88eb775,0xb954b867,0xba00b951,0xbad1ba23,0xbb18ba99,0xbbbcbb5a,0xbbc6bb7d,0xbbffbbf3,0xbc00bbf2,0xbb96bbe0,0xbbc2bbf0,0xba89bb22,
0xb0be8000,0xb1858000,0xb6e8b4b1,0xb7f3b570,0xb96bb87c,0xba19b91d,0xbae8ba3b,0xbb7fbae6,0xbbc9bb6e,0xbc00bbdd,0xbbfcbbf9,0xbb8ebbe5,0xbb7abbd1,0xba35bafc,0xba50baf9,0xb820b93e,
0xb0d78000,0xb19e8000,0xb70ab4c9,0xb80ab587,0xb982b891,0xba2db930,0xbafeba52,0xbb8ebaf9,0xbbd6bb80,0xbc00bbe6,0xbbf6bbfd,0xbb76bbda,0xbb5cbbc0,0xba00bad6,0xba15bacc,0xb79bb8fb,
0xb0f08000,0xb1b68000,0xb72cb4e1,0xb81ab59f,0xb999b8a6,0xba41b943,0xbb13ba69,0xbb9cbb0b,0xbbe0bb91,0xbbfebbed,0xbbeebc00,0xbb5cbbcd,0xbb3abbab,0xb9c9baae,0xb9d6ba9c,0xb6f4b8b5,
0xb1098000,0xb1cf8000,0xb74eb4f9,0xb82ab5b6,0xb9afb8ba,0xba54b956,0xbb27ba7f,0xbba9bb1d,0xbbe9bba0,0xbbfbbbf4,0xbbe3bc00,0xbb3fbbbe,0xbb16bb95,0xb990ba83,0xb994ba69,0xb648b86d,
0xb1228000,0xb1e88000,0xb76fb511,0xb83ab5ce,0xb9c5b8ce,0xba67b969,0xbb3aba95,0xbbb5bb2e,0xbbf1bbaf,0xbbf6bbf8,0xbbd7bbfe,0xbb21bbad,0xbaeebb7b,0xb954ba56,0xb94fba33,0xb599b822,
0xb13b8000,0xb2018000,0xb790b529,0xb84ab5e5,0xb9dab8e2,0xba7ab97b,0xbb4cbaaa,0xbbc0bb3e,0xbbf7bbbc,0xbbefbbfc,0xbbc8bbfb,0xbb01bb9b,0xbac4bb5f,0xb916ba27,0xb907b9fa,0xb4e7b7ac,
0xb1538000,0xb2198000,0xb7b2b540,0xb85ab5fd,0xb9f0b8f6,0xba8cb98d,0xbb5ebabf,0xbbcbbb4e,0xbbfcbbc9,0xbbe7bbff,0xbbb7bbf6,0xbadebb86,0xba97bb41,0xb8d6b9f6,0xb8bcb9be,0xb432b710,
0xb16c8000,0xb2328000,0xb7d2b558,0xb86ab614,0xba04b909,0xba9eb99f,0xbb6fbad3,0xbbd4bb5d,0xbbfebbd4,0xbbdebc00,0xbba3bbee,0xbababb70,0xba67bb20,0xb894b9c3,0xb86fb980,0xb2f7b670,
0x98b69248,0xa901a2ad,0x9d7f9bdb,0xadd5ac2b,0xa0529f12,0xb093af7e,0xa1e4a11b,0xb238b166,0xa376a2ad,0xb3d9b309,0xa484a420,0xb4bab454,0xa54da4e9,0xb584b520,0xa616a5b2,0xb64bb5e8,
0x9f1298b6,0xa998a376,0xa420a1e4,0xae84aca9,0xa67ba54d,0xb11cb02f,0xa86ba7a8,0xb2f0b207,0xa998a901,0xb460b3d9,0xaac5aa2f,0xb543b4d2,0xabf2ab5c,0xb622b5b3,0xac90ac44,0xb6fcb690,
0xa1e49bdb,0xaa2fa420,0xa6dfa4e9,0xaf33ad26,0xa966a86b,0xb1a4b09f,0xab5caa61,0xb3a8b2a7,0xaca9ac2b,0xb4d2b454,0xada3ad26,0xb5cbb54f,0xae9dae20,0xb6beb645,0xaf97af1a,0xb7a9b734,
0xa4209d7f,0xaac5a484,0xa8cfa6df,0xafe2ada3,0xab8eaa2f,0xb22cb10f,0xad26ac77,0xb42fb346,0xae84add5,0xb543b4ba,0xafe2af33,0xb651b5cb,0xb09fb048,0xb756b6d4,0xb14db0f6,0xb829b7d5,
0xa54d9f12,0xab5ca4e9,0xaa2fa86b,0xb048ae20,0xacdbabf2,0xb2b3b17f,0xae9dadbc,0xb48ab3e5,0xb02faf7e,0xb5b3b520,0xb10fb09f,0xb6d4b645,0xb1eeb17f,0xb7ebb761,0xb2ccb25d,0xb87bb839,
0xa67ba052,0xabf2a54d,0xab8ea966,0xb09fae9d,0xadeeacdb,0xb33ab1ee,0xb00aaf01,0xb4e4b441,0xb11cb093,0xb622b584,0xb22cb1a4,0xb756b6be,0xb33ab2b3,0xb83eb7eb,0xb423b3c0,0xb8cab885,
0xa7a8a11b,0xac44a5b2,0xac77aa61,0xb0f6af1a,0xaf01adbc,0xb3c0b25d,0xb0c5b023,0xb53db490,0xb207b166,0xb690b5e8,0xb346b2a7,0xb7d5b734,0xb441b3e5,0xb885b839,0xb4deb490,0xb917b8cf,
0xa86ba1e4,0xac90a616,0xad26ab5c,0xb14daf97,0xb00aae9d,0xb423b2cc,0xb17fb0c5,0xb596b4de,0xb2f0b238,0xb6fcb64b,0xb42fb3a8,0xb829b7a9,0xb4e4b48a,0xb8cab87b,0xb596b53d,0xb961b917,
0xacdba67b,0xaf33a8cf,0xb1a4b00a,0xb429b1fa,0xb466b33a,0xb66db54f,0xb5eeb52c,0xb846b783,0xb767b6ad,0xb93db8c5,0xb866b80e,0xba16b9ae,0xb90db8bb,0xbacbba75,0xb9a7b95c,0xbb5abb18,
0xad26a6df,0xaf7ea901,0xb1fab048,0xb454b238,0xb4a8b3a8,0xb6adb584,0xb645b579,0xb86eb7ca,0xb7d0b70d,0xb96ab8f0,0xb8a2b846,0xba44b9db,0xb94eb8fa,0xbaf7baa2,0xb9eab99e,0xbb7ebb40,
0xad71a744,0xafc9a934,0xb251b086,0xb47eb276,0xb4eab40b,0xb6ebb5b9,0xb69bb5c5,0xb895b809,0xb81cb76c,0xb995b919,0xb8dcb87e,0xba70ba08,0xb98cb936,0xbb1fbacd,0xba2ab9de,0xbb9ebb65,
0xadbca7a8,0xb00aa966,0xb2a7b0c5,0xb4a8b2b3,0xb52cb441,0xb729b5ee,0xb6f1b611,0xb8bbb82c,0xb84eb7ca,0xb9bfb942,0xb914b8b4,0xba9aba32,0xb9c8b971,0xbb44baf5,0xba66ba1a,0xbbbabb86,
0xae07a806,0xb02fa998,0xb2fdb103,0xb4d2b2f0,0xb56db478,0xb767b622,0xb745b65c,0xb8e1b84e,0xb880b813,0xb9e8b96a,0xb94bb8e8,0xbac1ba5b,0xba01b9a9,0xbb66bb1b,0xba9fba53,0xbbd1bba3,
0xae52a839,0xb055a9ca,0xb352b141,0xb4fcb32e,0xb5aeb4ae,0xb7a4b656,0xb799b6a7,0xb906b871,0xb8b1b841,0xba10b991,0xb981b91c,0xbae7ba82,0xba38b9e0,0xbb85bb3d,0xbad4ba8a,0xbbe3bbbc,
0xae9da86b,0xb07aa9fd,0xb3a8b17f,0xb526b36b,0xb5eeb4e4,0xb7e0b68a,0xb7ebb6f1,0xb92ab892,0xb8e1b86e,0xba36b9b7,0xb9b4b94e,0xbb0abaa8,0xba6cba14,0xbba0bb5d,0xbb04babc,0xbbf1bbd1,
0xaee8a89d,0xb09faa2f,0xb3fdb1bd,0xb54fb3a8,0xb62eb51a,0xb80eb6be,0xb81eb73a,0xb94eb8b4,0xb910b89a,0xba5bb9db,0xb9e6b97e,0xbb2cbacb,0xba9dba46,0xbbb8bb7b,0xbb31baec,0xbbfbbbe3,
0xb0c5aa61,0xb1eeabf2,0xb579b3e5,0xb6beb4e4,0xb82cb6f1,0xb90db83e,0xb971b8d4,0xba6cb9c8,0xba7fb9ff,0xbb66baf7,0xbb4bbaed,0xbbebbbb8,0xbbcdbb95,0xbbf4bc00,0xbbffbbf0,0xbb80bbca,
0xb0eaaa93,0xb213ac12,0xb5a2b411,0xb6e5b502,0xb849b724,0xb928b856,0xb993b8f5,0xba88b9e4,0xbaa1ba22,0xbb7cbb10,0xbb67bb0d,0xbbf4bbc8,0xbbdebbad,0xbbeabc00,0xbbffbbf9,0xbb5cbbb3,
0xb10faac5,0xb238ac2b,0xb5cbb42f,0xb70db520,0xb866b756,0xb942b86e,0xb9b4b914,0xbaa2b9ff,0xbac1ba44,0xbb90bb29,0xbb81bb2c,0xbbfbbbd6,0xbbebbbc1,0xbbdbbbfc,0xbbfbbbff,0xbb34bb98,
0xb134aaf8,0xb25dac44,0xb5f4b44e,0xb734b53d,0xb883b788,0xb95cb885,0xb9d5b934,0xbabcba1a,0xbae1ba65,0xbba3bb40,0xbb99bb48,0xbbffbbe3,0xbbf6bbd3,0xbbcabbf6,0xbbf2bc00,0xbb07bb7a,
0xb15aab2a,0xb282ac5e,0xb61db46c,0xb75cb55b,0xb89fb7ba,0xb975b89d,0xb9f5b953,0xbad5ba34,0xbafeba84,0xbbb4bb56,0xbbafbb62,0xbc00bbed,0xbbfcbbe2,0xbbb5bbed,0xbbe4bbfd,0xbad7bb57,
0xb17fab5c,0xb2a7ac77,0xb645b48a,0xb783b579,0xb8bbb7eb,0xb98eb8b4,0xba14b971,0xbaedba4e,0xbb1bbaa2,0xbbc3bb6b,0xbbc1bb7b,0xbbffbbf5,0xbc00bbee,0xbb9cbbe1,0xbbd2bbf6,0xbaa2bb31,
0xb1a4ab8e,0xb2ccac90,0xb66db4a8,0xb7a9b596,0xb8d7b80e,0xb9a7b8ca,0xba32b98e,0xbb04ba66,0xbb35bac0,0xbbd1bb7e,0xbbd2bb91,0xbbfbbbfb,0xbbffbbf7,0xbb80bbd2,0xbbbbbbeb,0xba6abb07,
0xb1c9abc0,0xb2f0aca9,0xb696b4c6,0xb7d0b5b3,0xb8f2b826,0xb9bfb8e1,0xba4fb9ab,0xbb1bba7f,0xbb4ebadc,0xbbddbb90,0xbbe0bba6,0xbbf5bbfe,0xbbfcbbfd,0xbb61bbc0,0xbba0bbdd,0xba2ebada,
0xb315acc2,0xb41dad8a,0xb7f6b5d1,0xb890b6b8,0xb9d7b8f7,0xba86b9a0,0xbb30ba96,0xbbb5bb39,0xbbe7bba1,0xbbfabbf6,0xbbecbc00,0xbb4cbbc1,0xbb3fbbab,0xb9bfba9f,0xb9efbaa9,0xb707b8b4,
0xb33aacdb,0xb42fada3,0xb80eb5ee,0xb8a2b6d4,0xb9efb90d,0xba9ab9b4,0xbb44baad,0xbbc1bb4b,0xbbefbbb0,0xbbf5bbfb,0xbbe0bbff,0xbb2dbbaf,0xbb19bb93,0xb983ba72,0xb9abba75,0xb656b869,
0xb35facf4,0xb441adbc,0xb821b60b,0xb8b4b6f1,0xba05b923,0xbaadb9c8,0xbb57bac3,0xbbcdbb5b,0xbbf6bbbe,0xbbeebbfe,0xbbd3bbfd,0xbb0cbb9c,0xbaf0bb78,0xb944ba42,0xb965ba3e,0xb5a2b81c,
0xb383ad0d,0xb454add5,0xb834b628,0xb8c5b70d,0xba1cb939,0xbac0b9db,0xbb69bad9,0xbbd6bb6b,0xbbfbbbcb,0xbbe5bc00,0xbbc2bbf8,0xbae9bb87,0xbac5bb5b,0xb903ba10,0xb91cba03,0xb4eab799,
0xb3a8ad26,0xb466adee,0xb846b645,0xb8d7b729,0xba32b94e,0xbad2b9ef,0xbb7bbaed,0xbbdfbb7a,0xbbfebbd6,0xbbdabc00,0xbbafbbf1,0xbac3bb6f,0xba96bb3b,0xb8c0b9db,0xb8cfb9c6,0xb42fb6f6,
0xb3cdad3f,0xb478ae07,0xb859b662,0xb8e8b745,0xba48b963,0xbae4ba01,0xbb8bbb01,0xbbe7bb88,0xbc00bbe0,0xbbcebbff,0xbb9abbe8,0xba9bbb56,0xba65bb18,0xb87bb9a5,0xb880b985,0xb2e4b651,
0xb3f1ad58,0xb48aae20,0xb86bb67f,0xb8fab761,0xba5db978,0xbaf5ba14,0xbb9abb15,0xbbeebb95,0xbc00bbe9,0xbbc0bbfc,0xbb82bbdd,0xba72bb3b,0xba30baf2,0xb834b96c,0xb82eb942,0xb166b5a8,
0xb40bad71,0xb49cae39,0xb87eb69b,0xb90bb77d,0xba72b98c,0xbb06ba26,0xbba8bb27,0xbbf4bba2,0xbbfebbf0,0xbbb0bbf9,0xbb68bbd0,0xba46bb1d,0xb9f9baca,0xb7d5b931,0xb7b4b8fc,0xafc9b4fc,
0x39b839ba,0x3a973ab5,0x39b339b5,0x3a583a78,0x39af39b1,0x3a153a37,0x39aa39ad,0x39cd39f2,0x39a639a8,0x398239a8,0x39a139a4,0x3933395b,0x399d399f,0x38e03909,0x3999399b,0x388938b5,
0xb979b972,0xb865b832,0xb986b980,0xb8c7b896,0xb994b98d,0xb924b8f6,0xb9a1b99b,0xb97db951,0xb9afb9a8,0xb9d2b9a8,0xb9bcb9b5,0xba21b9fa,0xb9c9b9c3,0xba6bba47,0xb9d6b9d0,0xbab0ba8e,
0xb9f4b9fe,0xbac7bae9,0xb9dfb9e9,0xba7ebaa3,0xb9c9b9d4,0xba2dba56,0xb9b3b9be,0xb9d6ba02,0xb99db9a8,0xb979b9a8,0xb986b992,0xb916b948,0xb970b97b,0xb8adb8e2,0xb958b964,0xb840b877,
0x39373927,0x381a37b7,0x39583948,0x38943858,0x39793969,0x390738ce,0x39993989,0x3974393e,0x39b839a8,0x39da39a8,0x39d639c7,0x3a393a0b,0x39f439e5,0x3a903a65,0x3a113a02,0x3ade3ab8,
0x3a2d3a3f,0x3af43b1a,0x3a093a1b,0x3aa23acc,0x39e339f6,0x3a453a74,0x39bc39d0,0x39df3a13,0x399439a8,0x397039a8,0x396b3980,0x38f83935,0x39413956,0x387a38ba,0x3916392b,0x37e83838,
0xb8f3b8d8,0xb79bb705,0xb929b90e,0xb85fb817,0xb95db943,0xb8eab8a6,0xb990b976,0xb96bb92b,0xb9c0b9a8,0xb9e3b9a8,0xb9f0b9d8,0xba50ba1b,0xba1dba07,0xbab3ba83,0xba49ba33,0xbb0abae0,
0xba64ba7c,0xbb1ebb46,0xba31ba4b,0xbac4baf3,0xb9fcba17,0xba5cba92,0xb9c5b9e1,0xb9e7ba23,0xb98bb9a8,0xb966b9a8,0xb94fb96d,0xb8dbb922,0xb911b930,0xb845b891,0xb8d1b8f1,0xb74eb7ee,
0x38ad3887,0x36ff364e,0x38f838d3,0x382a37ac,0x3941391d,0x38cc387c,0x39863964,0x39623918,0x39c939a8,0x39eb39a8,0x3a0939e9,0x3a673a2b,0x3a453a27,0x3ad53aa0,0x3a7e3a62,0x3b323b05,
0x3b453b6e,0x3bbc3bdd,0x3ae53b17,0x3b573b8f,0x3a733aae,0x3ac73b14,0x39f03a33,0x3a113a71,0x395d39a8,0x393739a8,0x38bc390e,0x384038bf,0x380f3867,0x365f3775,0x36af376a,0x341a3540,
0xb65fb593,0xb389b115,0xb7e8b726,0xb625b4f9,0xb8adb852,0xb830b748,0xb958b905,0xb933b8b5,0xb9f4b9a8,0xba15b9a8,0xba7eba3b,0xbad1ba78,0xbaf4babc,0xbb63bb20,0xbb57bb28,0xbbc6bb9b,
0xbb68bb91,0xbbd0bbed,0xbb04bb39,0xbb6fbba6,0xba89bac9,0xbadbbb2b,0xb9f8ba43,0xba19ba7f,0xb954b9a8,0xb92eb9a8,0xb89eb8fb,0xb820b8ab,0xb7b2b83d,0xb5ebb71b,0xb60eb6e3,0xb2deb4b1,
0x35bc34d5,0x32322f0e,0x377a369e,0x35b13469,0x388e3828,0x380f36ee,0x394f38f1,0x392938a0,0x39fc39a8,0x3a1d39a8,0x3a933a4b,0x3ae53a87,0x3b133ad6,0x3b7a3b36,0x3b783b49,0x3bd93bb1,
0x3b873baf,0x3be13bf8,0x3b213b58,0x3b853bbb,0x3a9e3ae3,0x3aee3b41,0x3a003a52,0x3a213a8e,0x394a39a8,0x392439a8,0x387f38e7,0x37fe3896,0x37423812,0x357636c1,0x356a3659,0x31853420,
0xb517b414,0xb0d7abd9,0xb70ab614,0xb53ab3ae,0xb86fb7f9,0xb7ddb693,0xb946b8dd,0xb91fb88c,0xba04b9a8,0xba25b9a8,0xbaa9ba5a,0xbaf7ba95,0xbb2fbaf0,0xbb90bb4b,0xbb96bb67,0xbbe8bbc4,
0xbba3bbc9,0xbbefbbff,0xbb3dbb74,0xbb9abbcd,0xbab3bafc,0xbb01bb55,0xba09ba62,0xba29ba9c,0xb941b9a8,0xb91bb9a8,0xb85fb8d3,0xb7bdb881,0xb6d2b7cd,0xb4ffb665,0xb4c3b5ce,0xb029b31b,
0x346f32a1,0x2ef52248,0x36993587,0x34c33288,0x385037a1,0x379b3637,0x393c38c9,0x39163877,0x3a0d39a8,0x3a2d39a8,0x3abd3a69,0x3b0a3aa3,0x3b4a3b08,0x3ba33b5f,0x3bb03b82,0x3bf43bd5,
0x3bf83c00,0x3bf93bd4,0x3bac3bdc,0x3be43bfe,0x3b133b69,0x3b543bab,0x3a313aaa,0x3a503ae0,0x391139a8,0x38ea39a8,0x377a386d,0x366b3817,0x34873608,0x313b348d,0x2d9731f4,0xad65291b,
0xac3828b6,0x2ec33365,0xb44bb160,0xb0bea57f,0xb759b5da,0xb648b45d,0xb90cb862,0xb8e5b80d,0xba35b9a8,0xba54b9a8,0xbb1bbab1,0xbb5cbae6,0xbbb5bb72,0xbbe9bbb2,0xbbfcbbe3,0xbbf5bc00,
0xbbfebbfc,0xbbefbbbc,0xbbbdbbe9,0xbbeebc00,0xbb24bb7b,0xbb63bbb9,0xba39bab8,0xba58baed,0xb907b9a8,0xb8e0b9a8,0xb737b858,0xb625b802,0xb40eb5ab,0xb042b42c,0xa9b1b0cb,0x30109a48,
0x25e4ad7e,0xb0beb475,0x33a23036,0x2f8ba3db,0x3715357c,0x360233f7,0x3902384d,0x38db37ee,0x3a3d39a8,0x3a5c39a8,0x3b2c3abf,0x3b6a3af3,0x3bc53b84,0x3bf23bc0,0x3bff3bee,0x3be93c00,
0x3c003bf4,0x3be23ba0,0x3bcc3bf3,0x3bf53bff,0x3b353b8c,0x3b713bc6,0x3a413ac6,0x3a603af9,0x38fd39a8,0x38d639a8,0x36f43842,0x35df37d8,0x3328354c,0x2e913396,0x16482f40,0xb16ca852,
0x251b304e,0x32193534,0xb2adae14,0xad972aac,0xb6d2b51d,0xb5bcb334,0xb8f8b838,0xb8d1b7c2,0xba45b9a8,0xba64b9a8,0xbb3dbacc,0xbb78baff,0xbbd3bb95,0xbbf8bbcb,0xbc00bbf7,0xbbdabbfd,
0xbbfebbe6,0xbbd2bb80,0xbbd9bbfa,0xbbfbbbfb,0xbb45bb9d,0xbb7fbbd1,0xba49bad3,0xba67bb05,0xb8f3b9a8,0xb8ccb9a8,0xb6afb82d,0xb599b7ac,0xb232b4ed,0xac9cb2d2,0x294dace7,0x32c62c83,
0xac06b1db,0xb371b5f1,0x31b62b75,0x2b43adb0,0x368d34bd,0x3576326f,0x38ee3822,0x38c73796,0x3a4d39a8,0x3a6b39a8,0x3b4c3ad9,0x3b853b0b,0x3bdf3ba4,0x3bfd3bd6,0x3bfc3bfd,0x3bc83bf8,
0x3bbd3b5a,0x3b473a99,0x3bfe3bf4,0x3bf93bbe,0x3b8b3bdb,0x3bb83bf7,0x3a6f3b11,0x3a8c3b3e,0x38c139a8,0x389939a8,0x35523780,0x343236cc,0x294d320d,0xad332de2,0xb40eaedc,0xb6a4b408,
0x346336aa,0x36f438b0,0xa6ad3004,0x2e2d3451,0xb52fb1aa,0xb40ead1a,0xb8bcb76a,0xb894b6b5,0xba73b9a8,0xba90b9a8,0xbb92bb17,0xbbbdbb43,0xbbffbbe0,0xbbf6bbf9,0xbbb2bbf0,0xbb35bbb4,
0xbba5bb30,0xbb21ba5e,0xbc00bbeb,0xbbf3bbaa,0xbb98bbe4,0xbbc2bbfb,0xba76bb1d,0xba93bb49,0xb8b7b9a8,0xb88eb9a8,0xb50bb753,0xb3d3b69e,0xa17fb147,0x2f27ac51,0x34b73099,0x37423499,
0xb50bb75e,0xb790b900,0x9cb6b12e,0xb010b4e1,0x34e730e4,0x33892b11,0x38b2373d,0x38893687,0x3a7a39a8,0x3a9739a8,0x3b9e3b22,0x3bc63b4e,0x3c003be8,0x3bef3bfd,0x3b983be5,0x3b0d3b9e,
0x3b893b02,0x3af73a1f,0x3c003bdf,0x3beb3b93,0x3ba33bec,0x3bcb3bfe,0x3a7e3b28,0x3a9b3b53,0x38ad39a8,0x388439a8,0x34c33726,0x33403670,0xa51b3080,0xb08d297f,0xb55eb1c3,0xb7ddb529,
0x35b13807,0x3815394d,0x28843257,0x31093570,0xb49fb01d,0xb2f7a7da,0xb8a8b710,0xb87fb659,0xba81b9a8,0xba9eb9a8,0xbba9bb2e,0xbbcfbb58,0xbbffbbef,0xbbe6bbff,0xbb7abbd7,0xbae1bb86,
0xbb6abad0,0xbacbb9dc,0xbbfdbbd0,0xbbe1bb79,0xbbaebbf2,0xbbd3bc00,0xba85bb33,0xbaa2bb5d,0xb8a3b9a8,0xb87ab9a8,0xb47bb6f9,0xb2adb642,0x2a7aaf72,0x3185a4b6,0x360232ea,0x383a35b6,
0xb654b85d,0xb85fb996,0xac38b37d,0xb201b5fd,0x34572eaa,0x32631e48,0x389e36e3,0x3874362b,0x3a8939a8,0x3aa539a8,0x3bb33b39,0x3bd73b62,0x3bfc3bf5,0x3bdc3c00,0x3b593bc7,0x3ab33b6b,
0x39b739b9,0x3a883aa6,0x39b239b4,0x3a483a68,0x39ae39b0,0x3a033a26,0x39a939ab,0x39bb39e0,0x39a539a7,0x396e3995,0x39a039a3,0x391e3947,0x399c399e,0x38ca38f5,0x3997399a,0x3873389f,
0xb97cb975,0xb87eb84c,0xb98ab983,0xb8deb8ae,0xb997b991,0xb93bb90d,0xb9a5b99e,0xb993b967,0xb9b2b9ab,0xb9e6b9bd,0xb9bfb9b9,0xba34ba0e,0xb9ccb9c6,0xba7dba59,0xb9d9b9d3,0xbac0ba9f,
0xb9efb9f9,0xbab6bad9,0xb9d9b9e4,0xba6aba91,0xb9c4b9cf,0xba18ba42,0xb9aeb9b9,0xb9bfb9ec,0xb997b9a3,0xb961b991,0xb981b98c,0xb8fcb92f,0xb96ab975,0xb892b8c8,0xb953b95e,0xb824b85c,
0x3940392f,0x383937f6,0x39613950,0x38b13876,0x39813971,0x392338eb,0x39a03991,0x398e395a,0x39bf39b0,0x39f339c1,0x39de39cf,0x3a4f3a22,0x39fb39ec,0x3aa43a7b,0x3a183a0a,0x3af03acb,
0x3a243a36,0x3ae13b07,0x39ff3a12,0x3a8b3ab7,0x39d939ec,0x3a2c3a5d,0x39b239c6,0x39c439f9,0x398a399e,0x3953398c,0x39613975,0x38d93917,0x3936394b,0x3859389a,0x390b3921,0x37a43816,
0xb901b8e6,0xb7e6b750,0xb936b91c,0xb883b83c,0xb96ab950,0xb90bb8c8,0xb99cb983,0xb98ab94b,0xb9ccb9b4,0xb9ffb9c6,0xb9fbb9e4,0xba6aba36,0xba28ba12,0xbacaba9b,0xba53ba3e,0xbb1dbaf5,
0xba57ba70,0xbb09bb33,0xba24ba3e,0xbaabbadc,0xb9efba0a,0xba40ba77,0xb9b7b9d3,0xb9c8ba05,0xb97cb99a,0xb944b988,0xb940b95e,0xb8b6b8fe,0xb901b921,0xb81eb86b,0xb8c0b8e1,0xb6fcb79e,
0x38c0389a,0x375636a7,0x390b38e6,0x38543800,0x3953392f,0x38f238a4,0x39973975,0x3985393d,0x39d939b9,0x3a0c39ca,0x3a1839f9,0x3a843a4a,0x3a533a36,0x3aed3abb,0x3a8b3a70,0x3b473b1c,
0x3b2e3b5a,0x3ba63bce,0x3aca3afe,0x3b373b74,0x3a533a91,0x3a9d3aef,0x39cc3a12,0x39de3a42,0x39363983,0x38fc3971,0x389238e6,0x37fb3880,0x37c5383c,0x35d136eb,0x3651370d,0x330934ae,
0xb6c3b5fa,0xb460b251,0xb824b788,0xb6b8b590,0xb8d9b880,0xb873b7d5,0xb981b92f,0xb96eb8f5,0xba18b9cf,0xba48b9e0,0xba9dba5d,0xbafabaa6,0xbb0fbad9,0xbb80bb43,0xbb6cbb40,0xbbd8bbb2,
0xbb51bb7d,0xbbbdbbe0,0xbae7bb1f,0xbb4ebb8c,0xba66baa9,0xbaafbb04,0xb9d1ba1e,0xb9e2ba4e,0xb928b97e,0xb8edb96c,0xb86eb8cd,0xb7afb866,0xb74bb80b,0xb54fb684,0xb5a2b679,0xb197b411,
0x362e3549,0x338330de,0x37e6370d,0x3651350e,0x38c0385c,0x38593788,0x397c3921,0x396a38e6,0x3a2439d3,0x3a5339e4,0x3ab63a70,0x3b0f3ab7,0x3b2e3af5,0x3b973b5a,0x3b8d3b61,0x3be83bc7,
0x3b703b9c,0x3bd03bef,0x3b033b3d,0x3b653ba2,0x3a793ac1,0x3ac03b19,0x39d53a2a,0x39e63a59,0x3919397a,0x38de3967,0x384938b4,0x3761384c,0x36cf37b4,0x34cc361d,0x34f035e2,0x302332e4,
0xb596b496,0xb244aecf,0xb783b690,0xb5e8b48a,0xb8a7b836,0xb83eb73a,0xb978b912,0xb965b8d7,0xba30b9d7,0xba5fb9e8,0xbacdba82,0xbb23bac8,0xbb4cbb10,0xbbacbb6f,0xbbaabb7f,0xbbf4bbd8,
0xbb8dbbb7,0xbbe0bbf9,0xbb1dbb5a,0xbb7abbb5,0xba8bbad9,0xbad0bb2d,0xb9d9ba36,0xb9eaba65,0xb90bb975,0xb8cfb963,0xb824b89a,0xb713b831,0xb651b750,0xb447b5b3,0xb43bb549,0xad58b1a4,
0x34fc33c0,0x31032bc0,0x371e3611,0x357e3405,0x388d3811,0x382436eb,0x39733903,0x396138c8,0x3a3c39db,0x3a6a39ec,0x3ae43a94,0x3b373ad9,0x3b673b2a,0x3bbe3b83,0x3bc33b9a,0x3bfc3be7,
0x3bed3bff,0x3bff3bea,0x3b8d3bc7,0x3bcc3bf5,0x3ae13b40,0x3b1d3b83,0x39ef3a70,0x39ff3a9b,0x38c0395e,0x3883394b,0x36c33816,0x357e3750,0x33833549,0x2e84332e,0x28cf3061,0xb0aca5b2,
0xaf7ea376,0x29663166,0xb514b2fd,0xb2bfad71,0xb809b69b,0xb734b555,0xb95cb8b9,0xb949b87b,0xba75b9f1,0xbaa1ba01,0xbb49bae9,0xbb8bbb25,0xbbcfbb96,0xbbf9bbd2,0xbc00bbf2,0xbbe3bbfe,
0xbbf6bc00,0xbbfcbbda,0xbb9fbbd6,0xbbd8bbfb,0xbaf0bb52,0xbb2cbb92,0xb9f3ba7b,0xba03baa6,0xb8b1b95a,0xb873b947,0xb673b7f6,0xb52cb718,0xb276b4de,0xac5eb251,0x2052ae39,0x321f2bf2,
0x2cf4a806,0xad3fb2d8,0x34a831ee,0x31e22a93,0x37db364b,0x36fc3502,0x395738a9,0x3944386b,0x3a8039f5,0x3aab3a05,0x3b5b3af8,0x3b993b33,0x3bdd3ba7,0x3bfd3bdd,0x3bff3bfa,0x3bd13bf9,
0x3bfd3bfd,0x3bf53bc6,0x3baf3be3,0x3be23bff,0x3b003b64,0x3b393ba0,0x39f73a86,0x3a083ab0,0x38a23955,0x38633942,0x362237bf,0x34d836e0,0x31663472,0x286b3172,0xaaf82b5c,0xb390ae84,
0xa8cf2cf4,0x2fc93423,0xb43bb0de,0xb103a484,0xb7a4b5fa,0xb6c3b4ae,0xb953b89a,0xb940b85c,0xba8bb9f9,0xbab6ba0a,0xbb6cbb07,0xbba6bb40,0xbbe8bbb7,0xbc00bbe7,0xbbfabbff,0xbbbabbf1,
0xbc00bbf6,0xbbebbbae,0xbbbebbed,0xbbebbc00,0xbb0fbb74,0xbb47bbad,0xb9fbba91,0xba0cbabb,0xb892b950,0xb854b93d,0xb5d1b788,0xb484b6a7,0xb055b405,0x9248b093,0x2e6ba484,0x347e3086,
0x98b6afe2,0xb128b4d8,0x339c2f97,0x3023a420,0x376c35a8,0x368a345a,0x394e388b,0x393b384c,0x3a9639fd,0x3ac03a0e,0x3b7c3b16,0x3bb33b4d,0x3bf23bc5,0x3c003bef,0x3bf03c00,0x3ba03be5,
0x3bde3b91,0x3b8a3af7,0x3bf23bff,0x3c003be3,0x3b533bb9,0x3b823bdf,0x3a103ac5,0x3a203aec,0x38443939,0x38033925,0x342f366d,0x31b03584,0xa8392f65,0xb15a1d7f,0xb531b1c9,0xb7e0b55b,
0x3269358a,0x35a83819,0xae842a61,0x205231e2,0xb651b405,0xb567b15a,0xb936b83c,0xb923b7f6,0xbacaba12,0xbaf0ba22,0xbbbebb5a,0xbbe3bb88,0xbbfdbbf5,0xbbddbc00,0xbb81bbd6,0xbadfbb7c,
0xbbcebb70,0xbb6dbac6,0xbbf8bbfb,0xbbffbbd6,0xbb60bbc4,0xbb8dbbe7,0xba14bacf,0xba24baf5,0xb834b934,0xb7e6b921,0xb3b4b634,0xb103b549,0x2c44ada3,0x326925b2,0x35e23309,0x384135f4,
0xb3a8b63a,0xb63fb869,0x2cc2ad58,0xa89db2f0,0x3617335f,0x352c30ac,0x3931382c,0x391e37d5,0x3ad43a16,0x3afa3a26,0x3bc93b66,0x3bea3b92,0x3bf93bfa,0x3bcf3bff,0x3b5f3bc5,0x3aad3b5d,
0x3bba3b4c,0x3b4d3a93,0x3bfc3bf6,0x3bfd3bc7,0x3b6c3bce,0x3b973bed,0x3a183ad9,0x3a283afe,0x3824392f,0x37c5391c,0x330935fa,0x3055350e,0xae6b2bc0,0xb377aa61,0xb690b423,0xb890b68a,
0x347236e5,0x36d438b6,0xa9fd2f7e,0x2c1233fd,0xb5dcb2b3,0xb4f0affb,0xb92db81c,0xb919b7b4,0xbaddba1a,0xbb03ba2a,0xbbd3bb72,0xbbf0bb9c,0xbbf2bbfe,0xbbbfbbfc,0xbb38bbaf,0xba77bb3c,
0xbba4bb23,0xbb2aba5b,0xbbffbbee,0xbbfabbb6,0xbb77bbd7,0xbba1bbf3,0xba1cbae2,0xba2cbb07,0xb813b92a,0xb7a4b917,0xb25db5bf,0xaf4cb4d2,0x3048a839,0x34412cf4,0x373a34c0,0x38dc371e,
0xb50eb78e,0xb767b901,0x24e9b0d1,0xadd5b484,0x35a23207,0x34b42e9d,0x3928380b,0x39143793,0x3ae73a1e,0x3b0c3a2e,0x3bdb3b7d,0x3bf53ba6,0x3be93c00,0x3bad3bf7,0x3b0d3b97,0x3a3e3b18,
0xb999b996,0xb889b85d,0xb99db99b,0xb8e0b8b5,0xb9a1b99f,0xb933b909,0xb9a6b9a4,0xb982b95b,0xb9aab9a8,0xb9cdb9a8,0xb9afb9ad,0xba15b9f2,0xb9b3b9b1,0xba58ba37,0xb9b8b9b5,0xba97ba78,
0xb9d6b9dc,0xbab0bad0,0xb9c9b9d0,0xba6bba8e,0xb9bcb9c3,0xba21ba47,0xb9afb9b5,0xb9d2b9fa,0xb9a1b9a8,0xb97db9a8,0xb994b99b,0xb924b951,0xb986b98d,0xb8c7b8f6,0xb979b980,0xb865b896,
0x3958394d,0x38403807,0x39703964,0x38ad3877,0x3986397b,0x391638e2,0x399d3992,0x39793948,0x39b339a8,0x39d639a8,0x39c939be,0x3a2d3a02,0x39df39d4,0x3a7e3a56,0x39f439e9,0x3ac73aa3,
0x3a113a1f,0x3ade3b02,0x39f43a02,0x3a903ab8,0x39d639e5,0x3a393a65,0x39b839c7,0x39da3a0b,0x399939a8,0x397439a8,0x39793989,0x3907393e,0x39583969,0x389438ce,0x39373948,0x381a3858,
0xb916b900,0xb7e8b75e,0xb941b92b,0xb87ab838,0xb96bb956,0xb8f8b8ba,0xb994b980,0xb970b935,0xb9bcb9a8,0xb9dfb9a8,0xb9e3b9d0,0xba45ba13,0xba09b9f6,0xbaa2ba74,0xba2dba1b,0xbaf4bacc,
0xba49ba5e,0xbb0abb30,0xba1dba33,0xbab3bae0,0xb9f0ba07,0xba50ba83,0xb9c0b9d8,0xb9e3ba1b,0xb990b9a8,0xb96bb9a8,0xb95db976,0xb8eab92b,0xb929b943,0xb85fb8a6,0xb8f3b90e,0xb79bb817,
0x38d138b0,0x374e36aa,0x391138f1,0x384537ee,0x394f3930,0x38db3891,0x398b396d,0x39663922,0x39c539a8,0x39e739a8,0x39fc39e1,0x3a5c3a23,0x3a313a17,0x3ac43a92,0x3a643a4b,0x3b1e3af3,
0x3a7e3a99,0x3b323b5a,0x3a453a62,0x3ad53b05,0x3a093a27,0x3a673aa0,0x39c939e9,0x39eb3a2b,0x398639a8,0x396239a8,0x39413964,0x38cc3918,0x38f8391d,0x382a387c,0x38ad38d3,0x36ff37ac,
0xb6afb5f1,0xb41ab1db,0xb80fb76a,0xb65fb540,0xb8bcb867,0xb840b775,0xb95db90e,0xb937b8bf,0xb9f0b9a8,0xba11b9a8,0xba73ba33,0xbac7ba71,0xbae5baae,0xbb57bb14,0xbb45bb17,0xbbbcbb8f,
0xbb57bb80,0xbbc6bbe6,0xbaf4bb28,0xbb63bb9b,0xba7ebabc,0xbad1bb20,0xb9f4ba3b,0xba15ba78,0xb958b9a8,0xb933b9a8,0xb8adb905,0xb830b8b5,0xb7e8b852,0xb625b748,0xb65fb726,0xb389b4f9,
0x360e3534,0x32de304e,0x37b236e3,0x35eb34b1,0x389e383d,0x3820371b,0x395438fb,0x392e38ab,0x39f839a8,0x3a1939a8,0x3a893a43,0x3adb3a7f,0x3b043ac9,0x3b6f3b2b,0x3b683b39,0x3bd03ba6,
0x3b783ba0,0x3bd93bf4,0x3b133b49,0x3b7a3bb1,0x3a933ad6,0x3ae53b36,0x39fc3a4b,0x3a1d3a87,0x394f39a8,0x392939a8,0x388e38f1,0x380f38a0,0x377a3828,0x35b136ee,0x35bc369e,0x32323469,
0xb56ab475,0xb185ad7e,0xb742b659,0xb576b420,0xb87fb812,0xb7feb6c1,0xb94ab8e7,0xb924b896,0xba00b9a8,0xba21b9a8,0xba9eba52,0xbaeeba8e,0xbb21bae3,0xbb85bb41,0xbb87bb58,0xbbe1bbbb,
0xbb96bbbc,0xbbe8bbfc,0xbb2fbb67,0xbb90bbc4,0xbaa9baf0,0xbaf7bb4b,0xba04ba5a,0xba25ba95,0xb946b9a8,0xb91fb9a8,0xb86fb8dd,0xb7ddb88c,0xb70ab7f9,0xb53ab693,0xb517b614,0xb0d7b3ae,
0x34c33365,0x302928b6,0x36d235ce,0x34ff331b,0x385f37cd,0x37bd3665,0x394138d3,0x391b3881,0x3a0939a8,0x3a2939a8,0x3ab33a62,0x3b013a9c,0x3b3d3afc,0x3b9a3b55,0x3ba33b74,0x3bef3bcd,
0x3bb03bd4,0x3bf43c00,0x3b4a3b82,0x3ba33bd5,0x3abd3b08,0x3b0a3b5f,0x3a0d3a69,0x3a2d3aa3,0x393c39a8,0x391639a8,0x385038c9,0x379b3877,0x369937a1,0x34c33637,0x346f3587,0x2ef53288,
0xad972248,0x2d6532a1,0xb487b1f4,0xb13ba91b,0xb77ab608,0xb66bb48d,0xb911b86d,0xb8eab817,0xba31b9a8,0xba50b9a8,0xbb13baaa,0xbb54bae0,0xbbacbb69,0xbbe4bbab,0xbbf8bbdc,0xbbf9bbfe,
0xbbfcbbff,0xbbf5bbc9,0xbbb5bbe3,0xbbe9bc00,0xbb1bbb72,0xbb5cbbb2,0xba35bab1,0xba54bae6,0xb90cb9a8,0xb8e5b9a8,0xb759b862,0xb648b80d,0xb44bb5da,0xb0beb45d,0xac38b160,0x2ec3a57f,
0x29b1abd9,0xb010b414,0x340e30cb,0x30421a48,0x373735ab,0x3625342c,0x39073858,0x38e03802,0x3a3939a8,0x3a5839a8,0x3b243ab8,0x3b633aed,0x3bbd3b7b,0x3bee3bb9,0x3bfe3be9,0x3bef3c00,
0x3bff3bf8,0x3be93baf,0x3bc53bee,0x3bf23c00,0x3b2c3b84,0x3b6a3bc0,0x3a3d3abf,0x3a5c3af3,0x390239a8,0x38db39a8,0x3715384d,0x360237ee,0x33a2357c,0x2f8b33f7,0x25e43036,0xb0bea3db,
0x96482f0e,0x316c34d5,0xb328af40,0xae912852,0xb6f4b54c,0xb5dfb396,0xb8fdb842,0xb8d6b7d8,0xba41b9a8,0xba60b9a8,0xbb35bac6,0xbb71baf9,0xbbccbb8c,0xbbf5bbc6,0xbc00bbf3,0xbbe2bbff,
0xbc00bbed,0xbbdabb91,0xbbd3bbf7,0xbbf8bbfd,0xbb3dbb95,0xbb78bbcb,0xba45bacc,0xba64baff,0xb8f8b9a8,0xb8d1b9a8,0xb6d2b838,0xb5bcb7c2,0xb2adb51d,0xad97b334,0x251bae14,0x32192aac,
0xa94db115,0xb2c6b593,0x32322ce7,0x2c9cac83,0x36af34ed,0x359932d2,0x38f3382d,0x38cc37ac,0x3a4939a8,0x3a6739a8,0x3b453ad3,0x3b7f3b05,0x3bd93b9d,0x3bfb3bd1,0x3bfe3bfa,0x3bd23bfb,
0x3bfc3bdd,0x3bc83b6e,0x3bdf3bfd,0x3bfd3bf8,0x3b4c3ba4,0x3b853bd6,0x3a4d3ad9,0x3a6b3b0b,0x38ee39a8,0x38c739a8,0x368d3822,0x35763796,0x31b634bd,0x2b43326f,0xac062b75,0xb371adb0,
0x340e364e,0x36a43887,0xa94d2edc,0x2d333408,0xb552b20d,0xb432ade2,0xb8c1b780,0xb899b6cc,0xba6fb9a8,0xba8cb9a8,0xbb8bbb11,0xbbb8bb3e,0xbbfebbdb,0xbbf9bbf7,0xbbbdbbf4,0xbb47bbbe,
0xbbb2bb46,0xbb35ba7c,0xbbffbbf0,0xbbf6bbb4,0xbb92bbe0,0xbbbdbbf9,0xba73bb17,0xba90bb43,0xb8bcb9a8,0xb894b9a8,0xb52fb76a,0xb40eb6b5,0xa6adb1aa,0x2e2dad1a,0x34633004,0x36f43451,
0xb4b7b705,0xb742b8d8,0x217fb099,0xaf27b499,0x350b3147,0x33d32c51,0x38b73753,0x388e369e,0x3a7639a8,0x3a9339a8,0x3b983b1d,0x3bc23b49,0x3c003be4,0x3bf33bfb,0x3ba53beb,0x3b213baa,
0x3b983b1a,0x3b0d3a3f,0x3c003be5,0x3bef3b9e,0x3b9e3be8,0x3bc63bfd,0x3a7a3b22,0x3a973b4e,0x38b239a8,0x388939a8,0x34e7373d,0x33893687,0x9cb630e4,0xb0102b11,0xb50bb12e,0xb790b4e1,
0x355e37b7,0x37dd3927,0x251b31c3,0x308d3529,0xb4c3b080,0xb340a97f,0xb8adb726,0xb884b670,0xba7eb9a8,0xba9bb9a8,0xbba3bb28,0xbbcbbb53,0xbc00bbec,0xbbebbbfe,0xbb89bbdf,0xbaf7bb93,
0xbb7abae9,0xbae1b9fe,0xbbffbbd7,0xbbe6bb86,0xbba9bbef,0xbbcfbbff,0xba81bb2e,0xba9ebb58,0xb8a8b9a8,0xb87fb9a8,0xb49fb710,0xb2f7b659,0x2884b01d,0x3109a7da,0x35b13257,0x38153570,
0xb602b832,0xb83ab972,0xaa7ab2ea,0xb185b5b6,0x347b2f72,0x32ad24b6,0x38a336f9,0x387a3642,0x3a8539a8,0x3aa239a8,0x3bae3b33,0x3bd33b5d,0x3bfd3bf2,0x3be13c00,0x3b6a3bd0,0x3acb3b79,
0x3b593ab5,0x3ab339ba,0x3bfc3bc7,0x3bdc3b6b,0x3bb33bf5,0x3bd73c00,0x3a893b39,0x3aa53b62,0x389e39a8,0x387439a8,0x345736e3,0x3263362b,0xac382eaa,0xb2011e48,0xb654b37d,0xb85fb5fd,
0xb99ab997,0xb89fb873,0xb99eb99c,0xb8f5b8ca,0xb9a3b9a0,0xb947b91e,0xb9a7b9a5,0xb995b96e,0xb9abb9a9,0xb9e0b9bb,0xb9b0b9ae,0xba26ba03,0xb9b4b9b2,0xba68ba48,0xb9b9b9b7,0xbaa6ba88,
0xb9d3b9d9,0xba9fbac0,0xb9c6b9cc,0xba59ba7d,0xb9b9b9bf,0xba0eba34,0xb9abb9b2,0xb9bdb9e6,0xb99eb9a5,0xb967b993,0xb991b997,0xb90db93b,0xb983b98a,0xb8aeb8de,0xb975b97c,0xb84cb87e,
0x395e3953,0x385c3824,0x3975396a,0x38c83892,0x398c3981,0x392f38fc,0x39a33997,0x39913961,0x39b939ae,0x39ec39bf,0x39cf39c4,0x3a423a18,0x39e439d9,0x3a913a6a,0x39f939ef,0x3ad93ab6,
0x3a0a3a18,0x3acb3af0,0x39ec39fb,0x3a7b3aa4,0x39cf39de,0x3a223a4f,0x39b039bf,0x39c139f3,0x399139a0,0x395a398e,0x39713981,0x38eb3923,0x39503961,0x387638b1,0x392f3940,0x37f63839,
0xb921b90b,0xb816b7a4,0xb94bb936,0xb89ab859,0xb975b961,0xb917b8d9,0xb99eb98a,0xb98cb953,0xb9c6b9b2,0xb9f9b9c4,0xb9ecb9d9,0xba5dba2c,0xba12b9ff,0xbab7ba8b,0xba36ba24,0xbb07bae1,
0xba3eba53,0xbaf5bb1d,0xba12ba28,0xba9bbaca,0xb9e4b9fb,0xba36ba6a,0xb9b4b9cc,0xb9c6b9ff,0xb983b99c,0xb94bb98a,0xb950b96a,0xb8c8b90b,0xb91cb936,0xb83cb883,0xb8e6b901,0xb750b7e6,
0x38e138c0,0x379e36fc,0x39213901,0x386b381e,0x395e3940,0x38fe38b6,0x399a397c,0x39883944,0x39d339b7,0x3a0539c8,0x3a0a39ef,0x3a773a40,0x3a3e3a24,0x3adc3aab,0x3a703a57,0x3b333b09,
0x3a703a8b,0x3b1c3b47,0x3a363a53,0x3abb3aed,0x39f93a18,0x3a4a3a84,0x39b939d9,0x39ca3a0c,0x39753997,0x393d3985,0x392f3953,0x38a438f2,0x38e6390b,0x38003854,0x389a38c0,0x36a73756,
0xb70db651,0xb4aeb309,0xb83cb7c5,0xb6ebb5d1,0xb8e6b892,0xb880b7fb,0xb983b936,0xb971b8fc,0xba12b9cc,0xba42b9de,0xba91ba53,0xbaefba9d,0xbafebaca,0xbb74bb37,0xbb5abb2e,0xbbcebba6,
0xbb40bb6c,0xbbb2bbd8,0xbad9bb0f,0xbb43bb80,0xba5dba9d,0xbaa6bafa,0xb9cfba18,0xb9e0ba48,0xb92fb981,0xb8f5b96e,0xb880b8d9,0xb7d5b873,0xb788b824,0xb590b6b8,0xb5fab6c3,0xb251b460,
0x367935a2,0x34113197,0x380b374b,0x3684354f,0x38cd386e,0x386637af,0x397e3928,0x396c38ed,0x3a1e39d1,0x3a4e39e2,0x3aa93a66,0x3b043aaf,0x3b1f3ae7,0x3b8c3b4e,0x3b7d3b51,0x3be03bbd,
0x3b613b8d,0x3bc73be8,0x3af53b2e,0x3b5a3b97,0x3a703ab6,0x3ab73b0f,0x39d33a24,0x39e43a53,0x3921397c,0x38e6396a,0x385c38c0,0x37883859,0x370d37e6,0x350e3651,0x3549362e,0x30de3383,
0xb5e2b4f0,0xb2e4b023,0xb7b4b6cf,0xb61db4cc,0xb8b4b849,0xb84cb761,0xb97ab919,0xb967b8de,0xba2ab9d5,0xba59b9e6,0xbac1ba79,0xbb19bac0,0xbb3dbb03,0xbba2bb65,0xbb9cbb70,0xbbefbbd0,
0xbb7fbbaa,0xbbd8bbf4,0xbb10bb4c,0xbb6fbbac,0xba82bacd,0xbac8bb23,0xb9d7ba30,0xb9e8ba5f,0xb912b978,0xb8d7b965,0xb836b8a7,0xb73ab83e,0xb690b783,0xb48ab5e8,0xb496b596,0xaecfb244,
0x3549343b,0x31a42d58,0x37503651,0x35b33447,0x389a3824,0x38313713,0x3975390b,0x396338cf,0x3a3639d9,0x3a6539ea,0x3ad93a8b,0x3b2d3ad0,0x3b5a3b1d,0x3bb53b7a,0x3bb73b8d,0x3bf93be0,
0x3b9a3bc3,0x3be73bfc,0x3b2a3b67,0x3b833bbe,0x3a943ae4,0x3ad93b37,0x39db3a3c,0x39ec3a6a,0x39033973,0x38c83961,0x3811388d,0x36eb3824,0x3611371e,0x3405357e,0x33c034fc,0x2bc03103,
0xb061a8cf,0x25b230ac,0xb549b383,0xb32eae84,0xb816b6c3,0xb750b57e,0xb95eb8c0,0xb94bb883,0xba70b9ef,0xba9bb9ff,0xbb40bae1,0xbb83bb1d,0xbbc7bb8d,0xbbf5bbcc,0xbbffbbed,0xbbeabbff,
0xbbf2bc00,0xbbfebbe3,0xbb96bbcf,0xbbd2bbf9,0xbae9bb49,0xbb25bb8b,0xb9f1ba75,0xba01baa1,0xb8b9b95c,0xb87bb949,0xb69bb809,0xb555b734,0xb2fdb514,0xad71b2bf,0xa376af7e,0x31662966,
0x2e39a052,0xabf2b21f,0x34de3276,0x32512c5e,0x37f63673,0x3718352c,0x395a38b1,0x39473873,0x3a7b39f3,0x3aa63a03,0x3b523af0,0x3b923b2c,0x3bd63b9f,0x3bfb3bd8,0x3c003bf6,0x3bda3bfc,
0x3bfa3bff,0x3bf93bd1,0x3ba73bdd,0x3bdd3bfd,0x3af83b5b,0x3b333b99,0x39f53a80,0x3a053aab,0x38a93957,0x386b3944,0x364b37db,0x350236fc,0x31ee34a8,0x2a9331e2,0xa8062cf4,0xb2d8ad3f,
0xab5c2af8,0x2e843390,0xb472b166,0xb172a86b,0xb7bfb622,0xb6e0b4d8,0xb955b8a2,0xb942b863,0xba86b9f7,0xbab0ba08,0xbb64bb00,0xbba0bb39,0xbbe3bbaf,0xbbffbbe2,0xbbfdbbfd,0xbbc6bbf5,
0xbbffbbfa,0xbbf1bbba,0xbbb7bbe8,0xbbe7bc00,0xbb07bb6c,0xbb40bba6,0xb9f9ba8b,0xba0abab6,0xb89ab953,0xb85cb940,0xb5fab7a4,0xb4aeb6c3,0xb0deb43b,0xa484b103,0x2cf4a8cf,0x34232fc9,
0x2484ae6b,0xb086b47e,0x34053055,0x30931248,0x378835d1,0x36a73484,0x39503892,0x393d3854,0x3a9139fb,0x3abb3a0c,0x3b743b0f,0x3bad3b47,0x3bed3bbe,0x3c003beb,0x3bf63c00,0x3bae3beb,
0x3c003bf0,0x3be53ba0,0x3bc53bf2,0x3bef3c00,0x3b163b7c,0x3b4d3bb3,0x39fd3a96,0x3a0e3ac0,0x388b394e,0x384c393b,0x35a8376c,0x345a368a,0x2f97339c,0xa4203023,0xafe298b6,0xb4d8b128,
0x31c93531,0x355b37e0,0xaf652839,0x9d7f315a,0xb66db42f,0xb584b1b0,0xb939b844,0xb925b803,0xbac5ba10,0xbaecba20,0xbbb9bb53,0xbbdfbb82,0xbbffbbf2,0xbbe3bc00,0xbb91bbde,0xbaf7bb8a,
0xbbd6bb81,0xbb7cbadf,0xbbf5bbfd,0xbc00bbdd,0xbb5abbbe,0xbb88bbe3,0xba12baca,0xba22baf0,0xb83cb936,0xb7f6b923,0xb405b651,0xb15ab567,0x2a61ae84,0x31e22052,0x358a3269,0x381935a8,
0xb309b5e2,0xb5f4b841,0x2da3ac44,0xa5b2b269,0x363433b4,0x35493103,0x39343834,0x392137e6,0x3acf3a14,0x3af53a24,0x3bc43b60,0x3be73b8d,0x3bfb3bf8,0x3bd63bff,0x3b703bce,0x3ac63b6d,
0x3bc53b5f,0x3b5d3aad,0x3bfa3bf9,0x3bff3bcf,0x3b663bc9,0x3b923bea,0x3a163ad4,0x3a263afa,0x382c3931,0x37d5391e,0x335f3617,0x30ac352c,0xad582cc2,0xb2f0a89d,0xb63ab3a8,0xb869b63f,
0x34233690,0x368a3890,0xabc02e6b,0x2a613377,0xb5fab309,0xb50eb055,0xb92fb824,0xb91cb7c5,0xbad9ba18,0xbafeba28,0xbbcebb6c,0xbbedbb97,0xbbf6bbfc,0xbbc7bbfd,0xbb4cbbba,0xba93bb4d,
0xbbafbb38,0xbb3cba77,0xbbfebbf2,0xbbfcbbbf,0xbb72bbd3,0xbb9cbbf0,0xba1abadd,0xba2abb03,0xb81cb92d,0xb7b4b919,0xb2b3b5dc,0xaffbb4f0,0x2f7ea9fd,0x33fd2c12,0x36e53472,0x38b636d4,
0xb4c0b73a,0xb71eb8dc,0x2839b048,0xacf4b441,0x35bf325d,0x34d22f4c,0x392a3813,0x391737a4,0x3ae23a1c,0x3b073a2c,0x3bd73b77,0x3bf33ba1,0x3bee3bff,0x3bb63bfa,0x3b233ba4,0x3a5b3b2a,
0x3b973b0d,0x3b183a3e,0x3c003be9,0x3bf73bad,0x3b7d3bdb,0x3ba63bf5,0x3a1e3ae7,0x3a2e3b0c,0x380b3928,0x37933914,0x320735a2,0x2e9d34b4,0xb0d124e9,0xb484add5,0xb78eb50e,0xb901b767,
0xb97239ba,0x39dc3996,0xb8323ab5,0x3ad0385d,0x3927b9fe,0xba1fb94d,0x37b7bae9,0xbb02b807,0xb8d83a3f,0x3a5e3900,0xb7053b1a,0x3b30375e,0x3887ba7c,0xba99b8b0,0x364ebb46,0xbb5ab6aa,
0xb90039dc,0x3a3f3972,0xad7e3be6,0x3bf83115,0x3807ba99,0xbae9b887,0xabd9bc00,0xbbfca248,0xb5f13b30,0x3b6e3705,0x32a13bed,0x3bd4b04e,0x3365bba0,0xbbc9b4d5,0xb593bbaf,0xbb803475,
0xb88739fe,0x3a99394d,0x35f13bbc,0x3b6eb414,0x3593bb1a,0xbb80b75e,0xb8b0bb02,0xba7c37b7,0xaf0e3bc9,0x3bf43365,0x3a1f39dc,0x3927b972,0xb04ebc00,0xbbed2248,0xbb30b85d,0xb7053ab5,
0xb8073a1f,0x3ae93927,0x39fe3a3f,0x394db900,0x31dbbb80,0xbbddb593,0xbb6eb832,0xb5f13ad0,0x31153c00,0x3be62248,0x3bff32a1,0x28b6bbd4,0xb7b7bb91,0xbb023534,0xbba0304e,0x34d53bed,
0xb7053a3f,0x3b303900,0x3bbc375e,0x3414bb1a,0x2248bbc9,0xbc00b365,0xbbdda8b6,0x31db3bff,0x36aa3bd4,0x3b46b2a1,0x3a7cb64e,0xb8b0bb5a,0xba1fba5e,0xb92738d8,0xb7b739fe,0x3b02394d,
0xb5f13a5e,0x3b6e38d8,0x3bd42bd9,0xb2a1bbfc,0xb115bbf4,0xbbe6af0e,0xb9dc375e,0x39723b1a,0x39273b46,0x3a1fb6aa,0x3475bad0,0xbbafb832,0xbb91b887,0xb5343a99,0x34143c00,0x3bbc2248,
0xb4d53a7c,0x3ba038b0,0x3a3fb593,0xb900bb80,0xb534bc00,0xbb912248,0xb4143ab5,0x3bbc385d,0x3a993a5e,0x3887b8d8,0xb5f1bbfc,0xbb6e2bd9,0xbbffb475,0x28b63baf,0x3ad03a1f,0x3832b927,
0xb3653a99,0x3bc93887,0x36aab996,0xbb46b9ba,0xb7b7bbed,0xbb02304e,0x34d53bfc,0x3ba02bd9,0x3b913927,0x3534ba1f,0xbae9ba3f,0xb8073900,0xbb5a28b6,0x364e3bff,0x3bd43115,0xb2a1bbe6,
0xb1153ab5,0x3be6385d,0xa8b6bb6e,0xbbffb5f1,0xb900bbbc,0xba3f3414,0x3a1f3b30,0x3927b705,0x3bfc375e,0x2bd9bb1a,0xbbedb475,0x304e3baf,0xb9ba3593,0x39963b80,0x3887b832,0xba99bad0,
0xad7e3ad0,0x3bf83832,0xb7b7bbff,0xbb0228b6,0xb9febb6e,0xb94d35f1,0x3bed3887,0x304eba99,0x3bd43414,0xb2a1bbbc,0xb9963534,0x39ba3b91,0xb6aa3900,0x3b463a3f,0xb115bba0,0xbbe6b4d5,
0xa2483ae9,0x3c003807,0xba99bb30,0xb8873705,0xbad0bb02,0xb83237b7,0x3b462d7e,0xb6aabbf8,0x3b1a28b6,0xb75ebbff,0xaf0e3a7c,0x3bf438b0,0xabd93ab5,0x3bfc385d,0xba5ebb5a,0xb8d8364e,
0x2bd93b02,0x3bfc37b7,0xbbedb927,0xb04e3a1f,0xbb6eba7c,0xb5f138b0,0x385db6aa,0xbab5bb46,0x39dcb1db,0xb972bbdd,0x38323c00,0x3ad02248,0x34d53bbc,0x3ba03414,0xbbf4b705,0x2f0e3b30,
0x304e3b1a,0x3bed375e,0xbb91b475,0x35343baf,0xbbd4b9dc,0xb2a13972,0x2248ba7c,0xbc00b8b0,0x3832b64e,0xbad0bb5a,0x3b803a99,0x3593b887,0x39003bfc,0x3a3fabd9,0xb9273414,0x3a1f3bbc,
0x32a13b30,0x3bd43705,0xb996304e,0x39ba3bed,0xbbffb927,0xa8b63a1f,0xb832bbf4,0xbad0af0e,0x3475b8b0,0xbbafba7c,0x3ba03593,0xb4d5bb80,0x3ae93b6e,0x3807b5f1,0x2bd93a99,0x3bfc3887,
0x34753b46,0x3baf36aa,0xb4d53832,0x3ba03ad0,0xbbedb85d,0x304e3ab5,0xbb30bb5a,0xb705364e,0x2248b9fe,0xbc00b94d,0x3887b414,0xba99bbbc,0x3be63a1f,0x3115b927,0x39dc3bf4,0x3972af0e,
0x35933b5a,0x3b80364e,0x31153a99,0x3be63887,0xbba0b705,0x34d53b30,0xbbf4b8d8,0x2f0e3a5e,0xb414bb02,0xbbbcb7b7,0xabd9ba1f,0xbbfcb927,0x3bd43832,0xb2a1bad0,0x3c003972,0xa248b9dc,
0x36aa3b6e,0x3b4635f1,0x38b03bdd,0x3a7c31db,0xbb1ab534,0x375e3b91,0xba3fb04e,0x39003bed,0xb807bbaf,0xbae9b475,0xb94dbbf8,0xb9fead7e,0x3ab53365,0xb85dbbc9,0x39ba28b6,0xb996bbff,
0x37b73b80,0x3b023593,0x3b1a3bc9,0x375eb365,0xba5eb2a1,0x38d83bd4,0xb53435f1,0x3b913b6e,0xb9babbfc,0xb996abd9,0xbbddbae9,0xb1db3807,0x38b0ad7e,0xba7cbbf8,0x28b6b900,0xbbffba3f,
0x385d3b91,0x3ab53534,0x3c003a5e,0x2248b8d8,0xb972ad7e,0x39dc3bf8,0x33653a3f,0x3bc93900,0xbb02bbe6,0xb7b73115,0xbb1ab6aa,0x375e3b46,0x3414b64e,0xbbbcbb5a,0xb94dbbdd,0xb9feb1db,
0x38d83ba0,0x3a5e34d5,0x3b3037b7,0xb705bb02,0xb85d28b6,0x3ab53bff,0x39ba3be6,0x39963115,0xbbc9bb6e,0xb36535f1,0xb6aa31db,0x3b463bdd,0xaf0eb94d,0xbbf4b9fe,0xbbf8bae9,0xad7e3807,
0x394d3baf,0x39fe3475,0x38d82d7e,0xba5ebbf8,0xb64e3115,0x3b5a3be6,0x3bd43b80,0x32a1b593,0xbbffba99,0x28b63887,0x336539ba,0x3bc93996,0xb75ebae9,0xbb1ab807,0xba3fb534,0x39003b91,
0x39ba3bbc,0x39963414,0x31dbb534,0xbbddbb91,0xb3653475,0x3bc93baf,0x3b803927,0xb593ba1f,0xbba0b972,0x34d539dc,0x3a3f3be6,0x39003115,0xb9febbd4,0xb94db2a1,0xb04e35f1,0x3bed3b6e,
0x3a1f3bc9,0x39273365,0xb475b972,0xbbafb9dc,0xabd9364e,0x3bfc3b5a,0x38d831db,0xba5ebbdd,0xbab5b807,0x385d3ae9,0x3c003b30,0x2248b705,0xbb80bbf4,0xb5932f0e,0x38b03b1a,0x3a7c375e,
0x3a7c3bd4,0x38b032a1,0xb972bb5a,0xb9dcb64e,0x2f0e3807,0x3bf43ae9,0x2d7eb534,0xbbf8bb91,0xb94db4d5,0x39fe3ba0,0x3a5e37b7,0xb8d8bb02,0xbc00bb46,0x224836aa,0x3bdd3bc9,0x31dbb365,
0x3ad03bdd,0x383231db,0xbb80bc00,0xb5932248,0x347538d8,0x3baf3a5e,0xb75eb9fe,0xbb1ab94d,0xb705ad7e,0x3b303bf8,0x3414af0e,0xbbbcbbf4,0xbb6eb9dc,0x35f13972,0x3ab538b0,0xb85dba7c,
0x3b1a3be6,0x375e3115,0xbbf4bb46,0x2f0e36aa,0x37053996,0x3b3039ba,0xbae9bbd4,0xb807b2a1,0xb1db304e,0x3bdd3bed,0xb64eb94d,0xbb5ab9fe,0xb9dcb7b7,0x39723b02,0x3365ad7e,0xbbc9bbf8,
0x3b5a3bed,0x364e304e,0xbab5b94d,0x385d39fe,0x38b03a3f,0x3a7c3900,0xbbffbba0,0x28b634d5,0x2d7e3593,0x3bf83b80,0xbb02bbc9,0xb7b7b365,0xb705b1db,0x3b303bdd,0xb807b9ba,0xbae9b996,
0x3b913bf4,0x35342f0e,0xb807b4d5,0x3ae93ba0,0x39ba3ad0,0x39963832,0xba99b972,0x388739dc,0x3593385d,0x3b803ab5,0xbbe6bb6e,0x311535f1,0xad7e304e,0x3bf83bed,0xbbafbbfc,0xb475abd9,
0x3bbc3bf8,0x34142d7e,0xabd92f0e,0x3bfc3bf4,0x3a993b46,0x388736aa,0xb64eb365,0x3b5a3bc9,0x38b039ba,0x3a7c3996,0xb972b85d,0x39dc3ab5,0x34753705,0x3baf3b30,0xbb1aba5e,0x375e38d8,
0x3bdd3bfc,0x31db2bd9,0x364e3807,0x3b5a3ae9,0x3b463ba0,0x36aa34d5,0x31153475,0x3be63baf,0x3a3f3ad0,0x39003832,0xad7e28b6,0x3bf83bff,0x38d83996,0x3a5e39ba,0xb534b2a1,0x3b913bd4,
0x3bf43bff,0x2f0e28b6,0x3a1f3a7c,0x392738b0,0x3bbc3bdd,0x341431db,0x394d39ba,0x39fe3996,0x3b5a3b91,0x364e3534,0x385d38d8,0x3ab53a5e,0x3ad03b1a,0x3832375e,0x36aa37b7,0x3b463b02,
0x3bff3c00,0x28b62248,0x3bc93bd4,0x336532a1,0x3bf83bfc,0x2d7e2bd9,0x3baf3bbc,0x34753414,0x3bed3bf4,0x304e2f0e,0x3b913ba0,0x353434d5,0x3bdd3be6,0x31db3115,0x3b6e3b80,0x35f13593,
0xb5933b6e,0x3b8035f1,0xb1153bdd,0x3be631db,0x34d5bb91,0xbba0b534,0x2f0ebbed,0xbbf4b04e,0xb4143baf,0x3bbc3475,0xabd93bf8,0x3bfc2d7e,0x32a1bbc9,0xbbd4b365,0x2248bbff,0xbc00a8b6,
0x37b73b46,0x3b02b6aa,0x3b1a3832,0x375ebad0,0xb8d8bab5,0xba5e385d,0xbb91b64e,0xb5343b5a,0x39ba39fe,0x3996b94d,0x3bdd3414,0x31dbbbbc,0xba7cb927,0xb8b03a1f,0xbbffaf0e,0xa8b63bf4,
0x3bd43534,0x32a1bb91,0x39bab8d8,0xb996ba5e,0xbbffad7e,0x28b63bf8,0xb8323a3f,0x3ad03900,0x3bafb115,0xb475bbe6,0x34d5bb46,0xbba0b6aa,0xbae9364e,0x38073b5a,0xabd93bdd,0x3bfc31db,
0x3a5eb75e,0xb8d8bb1a,0xb705bbaf,0xbb303475,0xb85d39dc,0x3ab53972,0x39ba3a7c,0x3996b8b0,0x3365bb5a,0xbbc9b64e,0xbb46b887,0xb6aa3a99,0x2f0e3bfc,0x3bf42bd9,0x3bf83414,0x2d7ebbbc,
0x2bd9bbaf,0xbbfcb475,0xbbedad7e,0x304e3bf8,0x35f13be6,0x3b6eb115,0x3ab5b593,0xb85dbb80,0xb9dcba99,0xb9723887,0xb83239ba,0x3ad03996,0x3ba03807,0x34d5bae9,0x2f0ebb91,0xbbf4b534,
0xb9babae9,0xb9963807,0xb1db3b30,0x3bdd3705,0x3bc937b7,0x3365bb02,0xb593bbf8,0xbb802d7e,0xbba028b6,0x34d53bff,0x3a3f3a7c,0x3900b8b0,0x394db85d,0xb9febab5,0xbbedb64e,0xb04e3b5a,
0xbbf8b365,0x2d7e3bc9,0x3b0239dc,0x37b7b972,0x39feb64e,0xb94dbb5a,0xbbedb1db,0x304e3bdd,0xb2a13ae9,0x3bd43807,0x39bab705,0xb996bb30,0xb6aabbf4,0xbb462f0e,0xb1153b1a,0x3be6375e,
0xb8b0385d,0x3a7c3ab5,0x39dcb5f1,0xb972bb6e,0xaf0ebbbc,0xbbf4b414,0xad7e3b30,0x3bf83705,0x39fe3b1a,0x394db75e,0xb8d8bbaf,0xba5e3475,0xbc00b593,0x22483b80,0x3bdd3832,0x31dbbad0,
0x33653bdd,0x3bc931db,0xb6aabc00,0xbb462248,0xbb02ba5e,0xb7b738d8,0x3ba0394d,0x34d5b9fe,0x3b912d7e,0xb534bbf8,0xbae92f0e,0x38073bf4,0xb64e3972,0x3b5a39dc,0x32a1ba7c,0xbbd4b8b0,
0x3b1a3a7c,0x375eb8b0,0xbbf4b593,0x2f0e3b80,0xbb30a248,0x37053c00,0x3807b85d,0xbae9bab5,0x31dbba5e,0xbbddb8d8,0x364e3bfc,0x3b5a2bd9,0x39723baf,0x39dcb475,0xbbc9b927,0xb3653a1f,
0x3b6e304e,0xb5f1bbed,0xb2a139fe,0x3bd4394d,0xb1153a3f,0x3be63900,0xb9dcbba0,0xb97234d5,0xba1fbb80,0xb9273593,0x3baf3365,0xb475bbc9,0x3b9131db,0xb534bbdd,0xb41439ba,0x3bbc3996,
0x3534b900,0xbb91ba3f,0x3ae93b1a,0x3807b75e,0x39ba3bc9,0x3996b365,0xba9928b6,0x38873bff,0xbb80b2a1,0x35933bd4,0xb115bb5a,0xbbe6b64e,0x2d7eba5e,0xbbf8b8d8,0x3baf39fe,0x3475b94d,
0xb807bbf8,0xbae9ad7e,0x39feaf0e,0xb94dbbf4,0x3bdd36aa,0xb1dbbb46,0x35f13bc9,0x3b6e3365,0xb11539ba,0x3be63996,0xbbffb85d,0x28b63ab5,0xbb02bb30,0xb7b73705,0x34d5b8d8,0xbba0ba5e,
0xbbddb9fe,0xb1db394d,0xb64ebbbc,0xbb5ab414,0x36aab75e,0xbb46bb1a,0x3be637b7,0xb115bb02,0x3a3f3bc9,0x3900b365,0xad7e39dc,0x3bf83972,0xba5ea248,0x38d83c00,0xbb91bab5,0xb534385d,
0xba3fa8b6,0x39003bff,0xbbf8b8b0,0x2d7e3a7c,0xb807bbdd,0xbae9b1db,0x2bd9b9ba,0xbbfcb996,0x3b6e3534,0xb5f1bb91,0x3bd43a5e,0x32a1b8d8,0x33653b1a,0x3bc9375e,0xb59337b7,0x3b803b02,
0xa8b63996,0x3bff39ba,0xb365385d,0x3bc93ab5,0xbbf8b9fe,0xad7e394d,0xbbafbae9,0xb4753807,0x304eb900,0xbbedba3f,0x3534b75e,0xbb91bb1a,0x3bdd3a7c,0x31dbb8b0,0x3b6e3b46,0x35f1b6aa,
0x39dc3c00,0x3972a248,0x3ad03bd4,0x3832b2a1,0xb9272bd9,0x3a1f3bfc,0xb7b73414,0x3b023bbc,0xba5ebbf4,0xb8d82f0e,0xbb30bba0,0xb70534d5,0x3887b115,0xba99bbe6,0x364eb593,0xbb5abb80,
0x3bf43972,0xaf0eb9dc,0x3a1f3115,0xb927bbe6,0x34143a99,0x3bbc3887,0x39fe3c00,0x394d2248,0xbb5ab705,0x364e3b30,0xb85d304e,0x3ab53bed,0xb832bba0,0xbad0b4d5,0xbb46bbaf,0xb6aa3475,
0x3887abd9,0xba99bbfc,0xb5f1bae9,0xbb6eb807,0x3b803ba0,0x3593b4d5,0x3a7c3475,0xb8b0bbaf,0xaf0e3832,0x3bf43ad0,0x3a1f3bff,0x392728b6,0xbbedb996,0x304e39ba,0xb70532a1,0x3b303bd4,
0xb414ba1f,0xbbbcb927,0xbbfcba3f,0x2bd93900,0x3a993593,0xb887bb80,0xb64ebad0,0xbb5ab832,0x3a7c3c00,0x38b02248,0x39dc32a1,0xb972bbd4,0xb4753534,0x3baf3b91,0x3b1a3bed,0x375eb04e,
0xbb30bbf4,0xb7052f0e,0xb41434d5,0x3bbc3ba0,0x2248b832,0xbc00bad0,0xbbddb9dc,0x31db3972,0x3b46385d,0xb6aabab5,0xb8b0bb6e,0xba7cb5f1,0x3a1f3bed,0x3927304e,0x37b7abd9,0xbb02bbfc,
0xbb5ab8d8,0x364e3a5e,0x3ab53bfc,0x385d2bd9,0xba7cbbf4,0xb8b0af0e,0xa8b6375e,0x3bff3b1a,0x2d7eb6aa,0xbbf8bb46,0xbb02b832,0x37b73ad0,0x3b303887,0xb705ba99,0xbae9bc00,0xb807a248,
0xb4d53115,0x3ba03be6,0x3a3f36aa,0xb900bb46,0xbb91b996,0x353439ba,0x3bbc3bd4,0x3414b2a1,0xba99bbed,0xb887b04e,0x35f139fe,0x3b6e394d,0xa8b6b7b7,0xbbffbb02,0xb832ad7e,0x3ad03bf8,
0x38323a99,0x3ad03887,0xb593b996,0xbb80b9ba,0xb475304e,0x3baf3bed,0x375e2bd9,0xbb1abbfc,0xbb30b927,0x37053a1f,0x3bbc3a3f,0xb414b900,0xbb6ebbff,0xb5f128b6,0x3ab53be6,0x385d3115,
0x3be63bd4,0x3115b2a1,0xbbffbb5a,0x28b6364e,0x39003ae9,0x3a3f3807,0xba1fbb91,0xb927b534,0xabd934d5,0x3bfc3ba0,0xb04eb7b7,0xbbedbb02,0xb9bab6aa,0x39963b46,0x38873365,0xba99bbc9,
0x3a1f3832,0xb927bad0,0xb47528b6,0x3baf3bff,0x3bfc3b6e,0xabd9b5f1,0xba5eb887,0x38d83a99,0x3ab53bbc,0x385d3414,0xbc00bb91,0x22483534,0x35933900,0x3b803a3f,0xba7cbba0,0xb8b0b4d5,
0x2248b414,0xbc00bbbc,0x3a993b91,0x38873534,0x38323475,0xbad0bbaf,0x36aa3927,0x3b463a1f,0x3b1a39dc,0xb75eb972,0xaf0e3115,0x3bf43be6,0x3bfc3bd4,0x2bd9b2a1,0xb8d8b5f1,0x3a5e3b6e,
0xb9febb02,0xb94db7b7,0x3a5e3927,0xb8d8ba1f,0xb64eb8b0,0xbb5aba7c,0x3bd43b46,0xb2a1b6aa,0x28b6b1db,0xbbffbbdd,0x3bc93c00,0x33652248,0x375e3414,0xbb1abbbc,0x3a3f3b30,0x39003705,
0xbbedbba0,0x304e34d5,0xb534b7b7,0xbb91bb02,0xbbd4bbff,0xb2a1a8b6,0x2248b115,0xbc00bbe6,0xbad0bb6e,0xb832b5f1,0x359331db,0xbb80bbdd,0xb900b9fe,0xba3fb94d,0x39273807,0xba1fbae9,
0xb85db705,0x3ab53b30,0xbc00bbed,0x2248304e,0xb9dcb927,0x39723a1f,0xbbc9bbf4,0xb365af0e,0xbb02ba7c,0x37b738b0,0xbb1abb80,0xb75eb593,0xbbbcbb6e,0x341435f1,0xb9feba99,0xb94db887,
0x34753593,0x3baf3b80,0xb4d5b365,0x3ba03bc9,0x304e32a1,0x3bed3bd4,0xb705b5f1,0x3b303b6e,0xa2482bd9,0x3c003bfc,0xb887b807,0x3a993ae9,0xb115ad7e,0x3be63bf8,0xb972b900,0x39dc3a3f,
0x3b463b5a,0x36aa364e,0x3a7c3a99,0x38b03887,0x3b1a3b30,0x375e3705,0x3a3f3a5e,0x390038d8,0x3ae93b02,0x380737b7,0x39fe3a1f,0x394d3927,0x3ab53ad0,0x385d3832,0x39ba39dc,0x39963972,
0x28b63c00,0x3bffa248,0x33653bd4,0x3bc9b2a1,0xad7ebbfc,0xbbf82bd9,0xb475bbbc,0xbbaf3414,0x304e3bf4,0x3bedaf0e,0x35343ba0,0x3b91b4d5,0xb1dbbbe6,0xbbdd3115,0xb5f1bb80,0xbb6e3593,
0x3bf4a8b6,0xaf0ebbff,0x3a1fb8b0,0xb927ba7c,0xbbbc31db,0x34143bdd,0xb94d3996,0x39fe39ba,0x3b5ab534,0xb64ebb91,0x385dba5e,0xbab5b8d8,0xbad0375e,0x38323b1a,0xb6aa3b02,0x3b4637b7,
0xb1dbbbfc,0xbbdd2bd9,0xbb5ab807,0xb64e3ae9,0x36aa3ba0,0x3b46b4d5,0x3be63475,0x3115bbaf,0xb900bad0,0xba3f3832,0xbbf8a8b6,0x2d7e3bff,0x3a5e3996,0x38d8b9ba,0x3b91b2a1,0xb534bbd4,
0xbbbc2d7e,0x34143bf8,0x2bd93bf4,0x3bfc2f0e,0x3a99b6aa,0xb887bb46,0xb64ebbc9,0xbb5a3365,0xb8b03996,0x3a7c39ba,0x39723ab5,0x39dcb85d,0x3475bb30,0xbbafb705,0xbb1ab8d8,0xb75e3a5e,
0x35343bf4,0x3b91af0e,0x3ae9b4d5,0xb807bba0,0xb996bad0,0xb9ba3832,0xb8873972,0x3a9939dc,0x3b80385d,0x3593bab5,0x3115bb6e,0xbbe6b5f1,0xbbf8b04e,0x2d7e3bed,0x34753bfc,0x3bafabd9,
0x3b5ab04e,0xb64ebbed,0xbab5b9fe,0xb85d394d,0xb8b03900,0x3a7c3a3f,0x3bff34d5,0x28b6bba0,0x2d7ebb80,0xbbf8b593,0xbb023365,0x37b73bc9,0x37053bdd,0x3b30b1db,0x3807b996,0xbae9b9ba,
0xb75ebbe6,0xbb1a3115,0xaf0e3b46,0x3bf436aa,0x3b303996,0x3705b9ba,0xb807bbd4,0xbae932a1,0xbbddb04e,0x31db3bed,0x3b5a394d,0x364eb9fe,0x3972b7b7,0xb9dcbb02,0xbbc9ad7e,0x33653bf8,
0xbad031db,0x38323bdd,0x3b802248,0xb593bc00,0x3475ba5e,0xbbafb8d8,0xb75e394d,0x3b1a39fe,0x37053bf8,0x3b30ad7e,0xb414bbf4,0xbbbcaf0e,0xbb6eb972,0xb5f139dc,0x3ab53a7c,0x385db8b0,
0x38b03bd4,0x3a7cb2a1,0xb9dcbb5a,0xb972364e,0xbbf4b807,0xaf0e3ae9,0x3bf83534,0xad7ebb91,0x39feb4d5,0xb94dbba0,0xb8d837b7,0x3a5e3b02,0xa2483b46,0x3c0036aa,0xb1dbbbc9,0xbbddb365,
0x3a1fb365,0xb927bbc9,0xb47539dc,0x3baf3972,0x2bd93b5a,0x3bfc364e,0xb8d8bbdd,0xba5e31db,0xbab5bae9,0xb85d3807,0x3c003705,0xa248bb30,0x3b802f0e,0xb593bbf4,0xb8b0375e,0x3a7c3b1a,
0xb996bbbc,0xb9ba3414,0x3bdd3534,0xb1dbbb91,0x3bc93475,0xb365bbaf,0xb5933927,0x3b803a1f,0xb4d53972,0x3ba039dc,0xb900bbe6,0xba3f3115,0xb94dbbd4,0xb9fe32a1,0x3bed35f1,0xb04ebb6e,
0xb94d3475,0x39fe3baf,0xb8d8bbf8,0xba5e2d7e,0xb64ebbe6,0xbb5ab115,0x3bd43593,0xb2a1bb80,0x3bff3887,0x28b6ba99,0xb3653996,0x3bc939ba,0xb75e3807,0x3b1a3ae9,0xba3fbb91,0xb9003534,
0x3a5e3ba0,0x38d8b4d5,0xb70537b7,0x3b303b02,0xbab5a8b6,0x385d3bff,0xb996bbe6,0xb9ba3115,0xb365bb6e,0xbbc9b5f1,0x3b4631db,0xb6aabbdd,0x3bf4394d,0x2f0eb9fe,0x2d7e3ae9,0x3bf83807,
0x385db534,0xbab5bb91,0x3c0038d8,0xa248ba5e,0x39723bf8,0x39dcad7e,0xb3653900,0x3bc93a3f,0xbb02b115,0x37b73be6,0xbb1abb46,0xb75e36aa,0xb414bb5a,0xbbbcb64e,0x394db1db,0xb9febbdd,
0xbb02bb80,0xb7b73593,0xb75ebbc9,0xbb1ab365,0x38d8b2a1,0xba5ebbd4,0x3b9135f1,0xb534bb6e,0x39963bfc,0x39baabd9,0x31db3ae9,0x3bdd3807,0xba7cad7e,0x38b03bf8,0xbbffb900,0x28b63a3f,
0xb6aa35f1,0x3b463b6e,0xb8b031db,0x3a7c3bdd,0xbb1abb91,0xb75e3534,0xba3fbbed,0xb900304e,0x3807b475,0xbae9bbaf,0x394dad7e,0xb9febbf8,0x3ab53bc9,0x385db365,0x39ba3bff,0x3996a8b6,
0x3b803b5a,0x3593b64e,0x3be63a99,0x3115b887,0xb4d53705,0x3ba03b30,0xaf0e38d8,0x3bf43a5e,0xbbbcbb02,0xb41437b7,0xbbfcba1f,0xabd93927,0x32a1b832,0xbbd4bad0,0x2248b972,0xbc00b9dc,
0x3475b6aa,0xbbafbb46,0xb4d5bad0,0xbba0b832,0x3bed3ab5,0x304eb85d,0x3b30364e,0xb705bb5a,0x2248394d,0x3c0039fe,0x38873bbc,0x3a993414,0xbbe6b927,0x31153a1f,0xb9dcaf0e,0x39723bf4,
0xbbd4bb30,0xb2a13705,0xb9bab04e,0x39963bed,0xa8b6b927,0xbbffba1f,0xbad0bbf4,0xb8322f0e,0x3baf38b0,0xb475ba7c,0x34d5b593,0xbba0bb80,0x38073b6e,0x3ae935f1,0x3bfc3a99,0x2bd9b887,
0xb04e375e,0x3bed3b1a,0x3b913baf,0x3534b475,0xbbd4b972,0x32a139dc,0x224838b0,0x3c003a7c,0xb832bb5a,0xbad0b64e,0xbb80b887,0x35933a99,0x39002bd9,0xba3fbbfc,0xb927bbbc,0xba1fb414,
0x3bfc3b02,0x2bd9b7b7,0xb04eb927,0xbbedba1f,0x35f13a7c,0x3b6e38b0,0x3ab536aa,0xb85dbb46,0xb972b1db,0x39dc3bdd,0x3ad03c00,0x3832a248,0xbba0bbbc,0xb4d53414,0xaf0e3705,0x3bf43b30,
0xa248b807,0xbc00bae9,0xba99b705,0x38873b30,0x3ad037b7,0xb832bb02,0xbb46bbf8,0xb6aa2d7e,0x3b1a3bff,0x375ea8b6,0xaf0eb8b0,0xbbf4ba7c,0x2bd9385d,0x3bfc3ab5,0x3a5e364e,0xb8d8bb5a,
0xbbf8bad0,0x2d7e3832,0x3b023bff,0x37b728b6,0xb94dbb6e,0xb9feb5f1,0x304e3887,0x3bed3a99,0x32a1b414,0xbbd4bbbc,0xb9bab534,0x39963b91,0x3b463900,0xb6aaba3f,0xbbe6bba0,0xb11534d5,
0x3115385d,0x3be63ab5,0x28b6b5f1,0xbbffbb6e,0xb900b414,0x3a3f3bbc,0x3a1f3705,0xb927bb30,0xbbfcbb1a,0x2bd9375e,0x3bed3baf,0x304eb475,0xb9babb80,0xb996b593,0x38873ad0,0x3a993832,
0x3bc93a99,0xb365b887,0xbb46b996,0x36aa39ba,0x3b023bed,0x37b7304e,0xbba0bbfc,0xb4d52bd9,0x35343927,0x3b913a1f,0xb807ba3f,0xbae9b900,0xb64ea8b6,0x3b5a3bff,0x32a1b115,0xbbd4bbe6,
0xb4d5b8b0,0xbba0ba7c,0x3a3f3b80,0x39003593,0x35342248,0xbb91bc00,0x3414385d,0x3bbc3ab5,0x3a9938d8,0xb887ba5e,0xb5f1abd9,0x3b6e3bfc,0x3bff3baf,0x28b6b475,0xbad0b927,0x38323a1f,
0xbb6eba5e,0x35f138d8,0x32a1abd9,0xbbd4bbfc,0xbbe6bbf4,0xb1152f0e,0x3972375e,0xb9dcbb1a,0xba1fbb46,0xb927b6aa,0x3baf3ad0,0xb475b832,0xb534b887,0xbb91ba99,0x3bbc3c00,0x3414a248,
0x37053900,0x3b303a3f,0xbbbcbb1a,0x3414375e,0x22483365,0x3c003bc9,0xbbddbbff,0xb1db28b6,0xb6aab2a1,0x3b463bd4,0xba7cbb5a,0xb8b0b64e,0xba1fb8d8,0x39273a5e,0xb7b7b94d,0xbb02b9fe,
0x3ae93a1f,0xb807b927,0x394d3a3f,0x39fe3900,0x3bdd3b80,0xb1dbb593,0x35f13832,0x3b6e3ad0,0x3be63c00,0x3115a248,0x28b632a1,0x3bff3bd4,0x3b023b91,0x37b73534,0xb4d5b04e,0x3ba03bed,
0xb887b94d,0xba99b9fe,0x35f13414,0xbb6ebbbc,0xb593b75e,0xbb80bb1a,0x38b037b7,0xba7cbb02,0xaf0eb365,0xbbf4bbc9,0x3a1f3972,0xb927b9dc,0x304e2248,0xbbedbc00,0x3b303ab5,0xb705b85d,
0xba3fb9dc,0x39003972,0xbbf8bbe6,0x2d7e3115,0xbae9ba99,0x38073887,0xbbfcbc00,0xabd92248,0xbb6ebb30,0x35f13705,0xbbd4bbed,0xb2a1b04e,0xbbc9bba0,0x336534d5,0xbb80bbaf,0xb593b475,
0x39723996,0x39dc39ba,0x3832385d,0x3ad03ab5,0x3927394d,0x3a1f39fe,0x37b73807,0x3b023ae9,0x38d83900,0x3a5e3a3f,0x3705375e,0x3b303b1a,0x388738b0,0x3a993a7c,0x364e36aa,0x3b5a3b46,
0x36aa3b5a,0x3b46b64e,0x38b03a99,0x3a7cb887,0xb75ebb30,0xbb1a3705,0xb900ba5e,0xba3f38d8,0x38073b02,0x3ae9b7b7,0x394d3a1f,0x39feb927,0xb85dbad0,0xbab53832,0xb996b9dc,0xb9ba3972,
0x3475bb80,0xbbafb593,0xb4d5bbc9,0xbba03365,0xb04e3bd4,0x3bed32a1,0x37053b6e,0x3b30b5f1,0xa248bbfc,0xbc00abd9,0xb887bae9,0xba993807,0x31153bf8,0x3be6ad7e,0x39723a3f,0x39dcb900,
0xbab53705,0x385d3b30,0xa2483bed,0x3c00304e,0x3972b927,0xb9dcba1f,0xb365bbf4,0xbbc92f0e,0xb7b73a7c,0x3b0238b0,0x375e3b80,0x3b1ab593,0x3414bb6e,0xbbbcb5f1,0xb94dba99,0xb9fe3887,
0x3bed34d5,0x304ebba0,0x3534bb02,0xbb91b7b7,0xbbd428b6,0x32a13bff,0x22483be6,0x3c003115,0x3ad0b5f1,0xb832bb6e,0xb593bbdd,0xbb8031db,0xb900394d,0x3a3f39fe,0x39273ae9,0x3a1fb807,
0xb94dbb02,0xb9fe37b7,0xb8d83927,0x3a5e3a1f,0x3b5a38b0,0x364eba7c,0x32a1bb46,0xbbd4b6aa,0xbbffb1db,0x28b63bdd,0x33653c00,0x3bc9a248,0x3b1ab414,0xb75ebbbc,0xb900bb30,0xba3f3705,
0x22483bbc,0x3c003414,0x3a99b534,0xb887bb91,0xb832bbaf,0xbad03475,0xb6aa3a1f,0x3b463927,0x3b1a3972,0x375eb9dc,0xaf0ebbe6,0xbbf4b115,0xbbfcb2a1,0x2bd93bd4,0x38d83b6e,0x3a5eb5f1,
0x3927b832,0xba1fbad0,0xbbafa8b6,0x34753bff,0xabd93b6e,0x3bfc35f1,0x38d8b887,0xba5eba99,0xb85dbbbc,0xbab53414,0xa2483b91,0x3c003534,0x3b803900,0x3593ba3f,0xb8b0bba0,0xba7c34d5,
0xbbe6b2a1,0x31153bd4,0x3bff364e,0x28b6bb5a,0x3900b807,0xba3fbae9,0xba1f3534,0x39273b91,0x2bd93ba0,0x3bfc34d5,0x304ebb02,0xbbedb7b7,0xb9babb46,0xb99636aa,0x38873bc9,0x3a99b365,
0x3ad03a99,0x3832b887,0xbb80b996,0xb59339ba,0xbbafb04e,0x34753bed,0x3b1aabd9,0xb75ebbfc,0x3705b927,0xbb30ba1f,0xb4143a3f,0x3bbc3900,0x35f13bff,0x3b6e28b6,0xb85dbbe6,0xbab53115,
0xb4d5bbe6,0xbba0b115,0x3a3f3b46,0x3900b6aa,0x3b9139ba,0x3534b996,0xbbbcb2a1,0x34143bd4,0xba99304e,0x38873bed,0x35f1b94d,0xbb6eb9fe,0x28b6bb02,0xbbffb7b7,0x38323bf8,0x3ad0ad7e,
0xb64e38d8,0x3b5a3a5e,0xb85dbbfc,0xbab52bd9,0xb8b0bbf4,0xba7c2f0e,0x3bff375e,0xa8b6bb1a,0x3bf836aa,0xad7ebb46,0xb7b73832,0x3b023ad0,0xb7053887,0x3b303a99,0xb807bc00,0xbae92248,
0x3b302f0e,0xb705bbf4,0x34143ba0,0x3bbc34d5,0x22483ad0,0x3c003832,0xbbddb972,0xb1db39dc,0xbb46bab5,0xb6aa385d,0x38b0b5f1,0xba7cbb6e,0x3a1fb04e,0xb927bbed,0x37b73bfc,0x3b022bd9,
0xbbbcba1f,0xb4143927,0x2bd9ba3f,0xbbfcb900,0x3887b593,0xba99bb80,0x3b5a3ad0,0x364eb832,0x38b03c00,0x3a7ca248,0xb97232a1,0x39dc3bd4,0xbbafb534,0x34753b91,0xb75ebbed,0xbb1ab04e,
0x38873bfc,0x3a992bd9,0xb5f13807,0x3b6e3ae9,0xbb80b4d5,0x35933ba0,0xba7cbbaf,0xb8b03475,0xaf0ebad0,0xbbf4b832,0x3a1fa8b6,0xb927bbff,0x3bed39ba,0x304eb996,0x37053bd4,0x3b3032a1,
0x2f0eb972,0xbbf4b9dc,0x3927b115,0xba1fbbe6,0x3bbc3a99,0x3414b887,0x394d3c00,0x39fea248,0xb64e3705,0x3b5a3b30,0xbab5b04e,0x385d3bed,0xbad0bba0,0xb83234d5,0xb6aabbaf,0xbb46b475,
0xb9dca248,0x39723c00,0xbad0b2a1,0x38323bd4,0xb927bbfc,0xba1fabd9,0xb7b7bbbc,0xbb02b414,0x3a5e2f0e,0xb8d8bbf4,0x3b3034d5,0xb705bba0,0x38873be6,0x3a993115,0x364e3b80,0x3b5a3593,
0x3bff3996,0xa8b6b9ba,0x3bc9385d,0xb365bab5,0x2d7e39fe,0x3bf8394d,0x34753ae9,0x3baf3807,0xbbedb900,0x304e3a3f,0xbb91b75e,0x35343b1a,0xb1dbba7c,0xbbddb8b0,0xb5f1bb46,0xbb6eb6aa,
0xba3fbbff,0xb90028b6,0xbbf8ba7c,0xad7e38b0,0x3807b1db,0xbae9bbdd,0xabd9b996,0xbbfcb9ba,0x3b6e3b91,0x35f1b534,0x3bd438d8,0xb2a1ba5e,0xb365375e,0x3bc93b1a,0x35933b02,0x3b8037b7,
0x31db39fe,0x3bdd394d,0x3b5a3bbc,0x364eb414,0xbb46b75e,0x36aa3b1a,0xb11537b7,0x3be63b02,0xb900bbc9,0xba3fb365,0xbbf8b9dc,0x2d7e3972,0x38d8a248,0xba5ebc00,0xb534bab5,0xbb91b85d,
0x3807ad7e,0xbae9bbf8,0xb9febbf4,0xb94daf0e,0x3bdd3b46,0x31dbb6aa,0x35f1b365,0xbb6ebbc9,0x31153996,0x3be639ba,0x3bff3ab5,0x28b6b85d,0xbb02b705,0x37b73b30,0x34d53a5e,0x3ba038d8,
0xbb91b900,0x35343a3f,0x38073b1a,0x3ae9375e,0xb996bbc9,0xb9bab365,0xb887a8b6,0x3a993bff,0x3593b2a1,0xbb80bbd4,0xbbe6bb5a,0xb115364e,0x3bf83a5e,0xad7eb8d8,0xb475b9fe,0xbbafb94d,
0x3b6e3bed,0x35f1b04e,0xb2a1b94d,0xbbd4b9fe,0x31153900,0x3be63a3f,0x39dc34d5,0xb972bba0,0xba1fb593,0x39273b80,0x3baf3bc9,0x3475b365,0xbb91bbdd,0xb53431db,0x34143996,0x3bbc39ba,
0xb75eba7c,0xbb1ab8b0,0xaf0e3593,0x3bf43b80,0x3705a248,0xbb30bc00,0xbae9b85d,0x38073ab5,0x3bdd3a5e,0xb1dbb8d8,0xbb5abbfc,0xb64e2bd9,0x39dc3baf,0x39723475,0xb365b927,0xbbc9ba1f,
0xb36531db,0x3bc93bdd,0x36aa2248,0xbb46bc00,0xbb02b8d8,0x37b73a5e,0x3ba039fe,0xb4d5b94d,0xbb91bbf8,0xb5342d7e,0x3ae93bf4,0x38072f0e,0xb64eb9dc,0xbb5ab972,0x32a138b0,0x3bd43a7c,
0x3a7c385d,0xb8b0bab5,0xb972b5f1,0x39dc3b6e,0x3bf43bbc,0x2f0eb414,0xbbf8bb30,0x2d7e3705,0x394d3b1a,0x39fe375e,0xba5ebbaf,0xb8d8b475,0xa2483593,0x3c003b80,0xb1dbb832,0xbbddbad0,
0xbbf8bbc9,0xad7e3365,0x3b023972,0xb7b7b9dc,0xb9febb5a,0xb94db64e,0x3bed3bdd,0x304eb1db,0xb2a1b807,0xbbd4bae9,0x39ba3b30,0x39963705,0x36aa2f0e,0xbb46bbf4,0x3115375e,0x3be63b1a,
0x39963ae9,0x39ba3807,0xbbddbb30,0x31db3705,0x336537b7,0x3bc93b02,0xbb80bbf8,0xb593ad7e,0xb4d5a8b6,0x3ba03bff,0xb900ba7c,0xba3fb8b0,0xb9feb85d,0x394d3ab5,0xb04eb64e,0xbbedbb5a,
0xabd9b475,0xbbfcbbaf,0x3bed3bf8,0x304ead7e,0x35f13115,0xbb6ebbe6,0x3ab53b80,0x385d3593,0x39dc3887,0xb972ba99,0x38323996,0x3ad039ba,0x3ba03ae9,0xb4d5b807,0x2f0e3534,0x3bf43b91,
0xb8d8b75e,0x3a5e3b1a,0xbb30bbaf,0xb705b475,0xbab5b9dc,0x385d3972,0xb996ba7c,0xb9bab8b0,0xbbc9bb5a,0x3365364e,0xb6aab887,0xbb46ba99,0xbbf4bbfc,0xaf0e2bd9,0xad7eb414,0xbbf8bbbc,
0x3bd43b91,0xb2a1b534,0x39ba3a5e,0x399638d8,0x3bff3bf8,0x28b6ad7e,0x38323900,0x3ad03a3f,0x3baf3be6,0x34753115,0x34d536aa,0x3ba03b46,0x3ae93b5a,0x3807364e,0x2bd931db,0x3bfc3bdd,
0xbb02bb46,0xb7b7b6aa,0xb75eb832,0xbb1abad0,0xba5ebab5,0xb8d8b85d,0xb534b64e,0xbb91bb5a,0xb996b9fe,0xb9bab94d,0xb1dbb414,0xbbddbbbc,0xb8b0b927,0xba7cba1f,0xa8b6af0e,0xbbffbbf4,
0x359335f1,0x3b803b6e,0x311531db,0x3be63bdd,0x34d53534,0x3ba03b91,0x2f0e304e,0x3bf43bed,0x34143475,0x3bbc3baf,0x2bd92d7e,0x3bfc3bf8,0x32a13365,0x3bd43bc9,0x224828b6,0x3c003bff,
0x80000,0x680060,0xc800c0,0x1280120,0xc0004,0x6c0064,0xcc00c4,0x12c0124,0x180010,0x780070,0xd800d0,0x1380130,0x1c0014,0x7c0074,0xdc00d4,0x13c0134,
0x1880180,0x1e801e0,0x2480240,0x2a802a0,0x18c0184,0x1ec01e4,0x24c0244,0x2ac02a4,0x1980190,0x1f801f0,0x2580250,0x2b802b0,0x19c0194,0x1fc01f4,0x25c0254,0x2bc02b4,
0x3080300,0x3680360,0x3c803c0,0x4280420,0x30c0304,0x36c0364,0x3cc03c4,0x42c0424,0x3180310,0x3780370,0x3d803d0,0x4380430,0x31c0314,0x37c0374,0x3dc03d4,0x43c0434,
0x4880480,0x4e804e0,0x5480540,0x5a805a0,0x48c0484,0x4ec04e4,0x54c0544,0x5ac05a4,0x4980490,0x4f804f0,0x5580550,0x5b805b0,0x49c0494,0x4fc04f4,0x55c0554,0x5bc05b4,
0x6080600,0x6680660,0x6c806c0,0x7280720,0x60c0604,0x66c0664,0x6cc06c4,0x72c0724,0x6180610,0x6780670,0x6d806d0,0x7380730,0x61c0614,0x67c0674,0x6dc06d4,0x73c0734,
0x7880780,0x7e807e0,0x8480840,0x8a808a0,0x78c0784,0x7ec07e4,0x84c0844,0x8ac08a4,0x7980790,0x7f807f0,0x8580850,0x8b808b0,0x79c0794,0x7fc07f4,0x85c0854,0x8bc08b4,
0x9080900,0x9680960,0x9c809c0,0xa280a20,0x90c0904,0x96c0964,0x9cc09c4,0xa2c0a24,0x9180910,0x9780970,0x9d809d0,0xa380a30,0x91c0914,0x97c0974,0x9dc09d4,0xa3c0a34,
0xa880a80,0xae80ae0,0xb480b40,0xba80ba0,0xa8c0a84,0xaec0ae4,0xb4c0b44,0xbac0ba4,0xa980a90,0xaf80af0,0xb580b50,0xbb80bb0,0xa9c0a94,0xafc0af4,0xb5c0b54,0xbbc0bb4,
0x280020,0x880080,0xe800e0,0x1480140,0x2c0024,0x8c0084,0xec00e4,0x14c0144,0x240020,0x840080,0xe400e0,0x1440140,0x800024,0xe00084,0x14000e4,0x1a00144,
0x1a801a0,0x2080200,0x2680260,0x2c802c0,0x1ac01a4,0x20c0204,0x26c0264,0x2cc02c4,0x1a401a0,0x2040200,0x2640260,0x2c402c0,0x20001a4,0x2600204,0x2c00264,0x32002c4,
0x3280320,0x3880380,0x3e803e0,0x4480440,0x32c0324,0x38c0384,0x3ec03e4,0x44c0444,0x3240320,0x3840380,0x3e403e0,0x4440440,0x3800324,0x3e00384,0x44003e4,0x4a00444,
0x4a804a0,0x5080500,0x5680560,0x5c805c0,0x4ac04a4,0x50c0504,0x56c0564,0x5cc05c4,0x4a404a0,0x5040500,0x5640560,0x5c405c0,0x50004a4,0x5600504,0x5c00564,0x62005c4,
0x6280620,0x6880680,0x6e806e0,0x7480740,0x62c0624,0x68c0684,0x6ec06e4,0x74c0744,0x6240620,0x6840680,0x6e406e0,0x7440740,0x6800624,0x6e00684,0x74006e4,0x7a00744,
0x7a807a0,0x8080800,0x8680860,0x8c808c0,0x7ac07a4,0x80c0804,0x86c0864,0x8cc08c4,0x7a407a0,0x8040800,0x8640860,0x8c408c0,0x80007a4,0x8600804,0x8c00864,0x92008c4,
0x9280920,0x9880980,0x9e809e0,0xa480a40,0x92c0924,0x98c0984,0x9ec09e4,0xa4c0a44,0x9240920,0x9840980,0x9e409e0,0xa440a40,0x9800924,0x9e00984,0xa4009e4,0xaa00a44,
0xaa80aa0,0xb080b00,0xb680b60,0xbc80bc0,0xaac0aa4,0xb0c0b04,0xb6c0b64,0xbcc0bc4,0xaa40aa0,0xb040b00,0xb640b60,0xbc40bc0,0xb000aa4,0xb600b04,0xbc00b64,0x300bc4,
0x300030,0x900090,0xf000f0,0x1500150,0x900034,0xf00094,0x15000f4,0x1b00154,0x340030,0x940090,0xf400f0,0x1540150,0x900034,0xf00094,0x15000f4,0x1b00154,
0x1b001b0,0x2100210,0x2700270,0x2d002d0,0x21001b4,0x2700214,0x2d00274,0x33002d4,0x1b401b0,0x2140210,0x2740270,0x2d402d0,0x21001b4,0x2700214,0x2d00274,0x33002d4,
0x3300330,0x3900390,0x3f003f0,0x4500450,0x3900334,0x3f00394,0x45003f4,0x4b00454,0x3340330,0x3940390,0x3f403f0,0x4540450,0x3900334,0x3f00394,0x45003f4,0x4b00454,
0x4b004b0,0x5100510,0x5700570,0x5d005d0,0x51004b4,0x5700514,0x5d00574,0x63005d4,0x4b404b0,0x5140510,0x5740570,0x5d405d0,0x51004b4,0x5700514,0x5d00574,0x63005d4,
0x6300630,0x6900690,0x6f006f0,0x7500750,0x6900634,0x6f00694,0x75006f4,0x7b00754,0x6340630,0x6940690,0x6f406f0,0x7540750,0x6900634,0x6f00694,0x75006f4,0x7b00754,
0x7b007b0,0x8100810,0x8700870,0x8d008d0,0x81007b4,0x8700814,0x8d00874,0x93008d4,0x7b407b0,0x8140810,0x8740870,0x8d408d0,0x81007b4,0x8700814,0x8d00874,0x93008d4,
0x9300930,0x9900990,0x9f009f0,0xa500a50,0x9900934,0x9f00994,0xa5009f4,0xab00a54,0x9340930,0x9940990,0x9f409f0,0xa540a50,0x9900934,0x9f00994,0xa5009f4,0xab00a54,
0xab00ab0,0xb100b10,0xb700b70,0xbd00bd0,0xb100ab4,0xb700b14,0xbd00b74,0x380bd4,0xab40ab0,0xb140b10,0xb740b70,0xbd40bd0,0xb100ab4,0xb700b14,0xbd00b74,0x380bd4,
0x380038,0x980098,0xf800f8,0x1580158,0x98003c,0xf8009c,0x15800fc,0x1b8015c,0x3c0038,0x9c0098,0xfc00f8,0x15c0158,0x98003c,0xf8009c,0x15800fc,0x1b8015c,
0x1b801b8,0x2180218,0x2780278,0x2d802d8,0x21801bc,0x278021c,0x2d8027c,0x33802dc,0x1bc01b8,0x21c0218,0x27c0278,0x2dc02d8,0x21801bc,0x278021c,0x2d8027c,0x33802dc,
0x3380338,0x3980398,0x3f803f8,0x4580458,0x398033c,0x3f8039c,0x45803fc,0x4b8045c,0x33c0338,0x39c0398,0x3fc03f8,0x45c0458,0x398033c,0x3f8039c,0x45803fc,0x4b8045c,
0x4b804b8,0x5180518,0x5780578,0x5d805d8,0x51804bc,0x578051c,0x5d8057c,0x63805dc,0x4bc04b8,0x51c0518,0x57c0578,0x5dc05d8,0x51804bc,0x578051c,0x5d8057c,0x63805dc,
0x6380638,0x6980698,0x6f806f8,0x7580758,0x698063c,0x6f8069c,0x75806fc,0x7b8075c,0x63c0638,0x69c0698,0x6fc06f8,0x75c0758,0x698063c,0x6f8069c,0x75806fc,0x7b8075c,
0x7b807b8,0x8180818,0x8780878,0x8d808d8,0x81807bc,0x878081c,0x8d8087c,0x93808dc,0x7bc07b8,0x81c0818,0x87c0878,0x8dc08d8,0x81807bc,0x878081c,0x8d8087c,0x93808dc,
0x9380938,0x9980998,0x9f809f8,0xa580a58,0x998093c,0x9f8099c,0xa5809fc,0xab80a5c,0x93c0938,0x99c0998,0x9fc09f8,0xa5c0a58,0x998093c,0x9f8099c,0xa5809fc,0xab80a5c,
0xab80ab8,0xb180b18,0xb780b78,0xbd80bd8,0xb180abc,0xb780b1c,0xbd80b7c,0x400bdc,0xabc0ab8,0xb1c0b18,0xb7c0b78,0xbdc0bd8,0xb180abc,0xb780b1c,0xbd80b7c,0x400bdc,
0xacc0acc,0xb2c0b2c,0xb8c0b8c,0xbec0bec,0xb2c0acc,0xb8c0b8c,0xbec0b8c,0x500050,0xacc0acc,0xb2c0b2c,0xb8c0b8c,0xbec0bec,0xb2c0b2c,0xb8c0b8c,0xbec0bec,0x500050,
0x94c094c,0x9ac09ac,0xa0c0a0c,0xa6c0a6c,0x9ac094c,0xa0c0a0c,0xa6c0a0c,0xacc0acc,0x94c094c,0x9ac09ac,0xa0c0a0c,0xa6c0a6c,0x9ac09ac,0xa0c0a0c,0xa6c0a6c,0xacc0acc,
0x7cc07cc,0x82c082c,0x88c088c,0x8ec08ec,0x82c07cc,0x88c088c,0x8ec088c,0x94c094c,0x7cc07cc,0x82c082c,0x88c088c,0x8ec08ec,0x82c082c,0x88c088c,0x8ec08ec,0x94c094c,
0x64c064c,0x6ac06ac,0x70c070c,0x76c076c,0x6ac064c,0x70c070c,0x76c070c,0x7cc07cc,0x64c064c,0x6ac06ac,0x70c070c,0x76c076c,0x6ac06ac,0x70c070c,0x76c076c,0x7cc07cc,
0x4cc04cc,0x52c052c,0x58c058c,0x5ec05ec,0x52c04cc,0x58c058c,0x5ec058c,0x64c064c,0x4cc04cc,0x52c052c,0x58c058c,0x5ec05ec,0x52c052c,0x58c058c,0x5ec05ec,0x64c064c,
0x34c034c,0x3ac03ac,0x40c040c,0x46c046c,0x3ac034c,0x40c040c,0x46c040c,0x4cc04cc,0x34c034c,0x3ac03ac,0x40c040c,0x46c046c,0x3ac03ac,0x40c040c,0x46c046c,0x4cc04cc,
0x1cc01cc,0x22c022c,0x28c028c,0x2ec02ec,0x22c01cc,0x28c028c,0x2ec028c,0x34c034c,0x1cc01cc,0x22c022c,0x28c028c,0x2ec02ec,0x22c022c,0x28c028c,0x2ec02ec,0x34c034c,
0x4c004c,0xac00ac,0x10c010c,0x16c016c,0xac004c,0x10c010c,0x16c010c,0x1cc01cc,0x4c004c,0xac00ac,0x10c010c,0x16c016c,0xac00ac,0x10c010c,0x16c016c,0x1cc01cc,
0xac80ac8,0xb280b28,0xb880b88,0xbe80be8,0xb280ac8,0xb880b88,0xbe80b88,0x4c004c,0xac80ac8,0xb280b28,0xb880b88,0xbe80be8,0xb280b28,0xb880b88,0xbe80be8,0x4c004c,
0x9480948,0x9a809a8,0xa080a08,0xa680a68,0x9a80948,0xa080a08,0xa680a08,0xac80ac8,0x9480948,0x9a809a8,0xa080a08,0xa680a68,0x9a809a8,0xa080a08,0xa680a68,0xac80ac8,
0x7c807c8,0x8280828,0x8880888,0x8e808e8,0x82807c8,0x8880888,0x8e80888,0x9480948,0x7c807c8,0x8280828,0x8880888,0x8e808e8,0x8280828,0x8880888,0x8e808e8,0x9480948,
0x6480648,0x6a806a8,0x7080708,0x7680768,0x6a80648,0x7080708,0x7680708,0x7c807c8,0x6480648,0x6a806a8,0x7080708,0x7680768,0x6a806a8,0x7080708,0x7680768,0x7c807c8,
0x4c804c8,0x5280528,0x5880588,0x5e805e8,0x52804c8,0x5880588,0x5e80588,0x6480648,0x4c804c8,0x5280528,0x5880588,0x5e805e8,0x5280528,0x5880588,0x5e805e8,0x6480648,
0x3480348,0x3a803a8,0x4080408,0x4680468,0x3a80348,0x4080408,0x4680408,0x4c804c8,0x3480348,0x3a803a8,0x4080408,0x4680468,0x3a803a8,0x4080408,0x4680468,0x4c804c8,
0x1c801c8,0x2280228,0x2880288,0x2e802e8,0x22801c8,0x2880288,0x2e80288,0x3480348,0x1c801c8,0x2280228,0x2880288,0x2e802e8,0x2280228,0x2880288,0x2e802e8,0x3480348,
0x480048,0xa800a8,0x1080108,0x1680168,0xa80048,0x1080108,0x1680108,0x1c801c8,0x480048,0xa800a8,0x1080108,0x1680168,0xa800a8,0x1080108,0x1680168,0x1c801c8,
0xac40ac4,0xb240b24,0xb840b84,0xbe40be4,0xb240ac4,0xb840b84,0xbe40b84,0x480048,0xac40ac4,0xb240b24,0xb840b84,0xbe40be4,0xb240b24,0xb840b84,0xbe40be4,0x480048,
0x9440944,0x9a409a4,0xa040a04,0xa640a64,0x9a40944,0xa040a04,0xa640a04,0xac40ac4,0x9440944,0x9a409a4,0xa040a04,0xa640a64,0x9a409a4,0xa040a04,0xa640a64,0xac40ac4,
0x7c407c4,0x8240824,0x8840884,0x8e408e4,0x82407c4,0x8840884,0x8e40884,0x9440944,0x7c407c4,0x8240824,0x8840884,0x8e408e4,0x8240824,0x8840884,0x8e408e4,0x9440944,
0x6440644,0x6a406a4,0x7040704,0x7640764,0x6a40644,0x7040704,0x7640704,0x7c407c4,0x6440644,0x6a406a4,0x7040704,0x7640764,0x6a406a4,0x7040704,0x7640764,0x7c407c4,
0x4c404c4,0x5240524,0x5840584,0x5e405e4,0x52404c4,0x5840584,0x5e40584,0x6440644,0x4c404c4,0x5240524,0x5840584,0x5e405e4,0x5240524,0x5840584,0x5e405e4,0x6440644,
0x3440344,0x3a403a4,0x4040404,0x4640464,0x3a40344,0x4040404,0x4640404,0x4c404c4,0x3440344,0x3a403a4,0x4040404,0x4640464,0x3a403a4,0x4040404,0x4640464,0x4c404c4,
0x1c401c4,0x2240224,0x2840284,0x2e402e4,0x22401c4,0x2840284,0x2e40284,0x3440344,0x1c401c4,0x2240224,0x2840284,0x2e402e4,0x2240224,0x2840284,0x2e402e4,0x3440344,
0x440044,0xa400a4,0x1040104,0x1640164,0xa40044,0x1040104,0x1640104,0x1c401c4,0x440044,0xa400a4,0x1040104,0x1640164,0xa400a4,0x1040104,0x1640164,0x1c401c4,
0xac00ac0,0xb200b20,0xb800b80,0xbe00be0,0xb200ac0,0xb800b80,0xbe00b80,0x440044,0xac00ac0,0xb200b20,0xb800b80,0xbe00be0,0xb200b20,0xb800b80,0xbe00be0,0x440044,
0x9400940,0x9a009a0,0xa000a00,0xa600a60,0x9a00940,0xa000a00,0xa600a00,0xac00ac0,0x9400940,0x9a009a0,0xa000a00,0xa600a60,0x9a009a0,0xa000a00,0xa600a60,0xac00ac0,
0x7c007c0,0x8200820,0x8800880,0x8e008e0,0x82007c0,0x8800880,0x8e00880,0x9400940,0x7c007c0,0x8200820,0x8800880,0x8e008e0,0x8200820,0x8800880,0x8e008e0,0x9400940,
0x6400640,0x6a006a0,0x7000700,0x7600760,0x6a00640,0x7000700,0x7600700,0x7c007c0,0x6400640,0x6a006a0,0x7000700,0x7600760,0x6a006a0,0x7000700,0x7600760,0x7c007c0,
0x4c004c0,0x5200520,0x5800580,0x5e005e0,0x52004c0,0x5800580,0x5e00580,0x6400640,0x4c004c0,0x5200520,0x5800580,0x5e005e0,0x5200520,0x5800580,0x5e005e0,0x6400640,
0x3400340,0x3a003a0,0x4000400,0x4600460,0x3a00340,0x4000400,0x4600400,0x4c004c0,0x3400340,0x3a003a0,0x4000400,0x4600460,0x3a003a0,0x4000400,0x4600460,0x4c004c0,
0x1c001c0,0x2200220,0x2800280,0x2e002e0,0x22001c0,0x2800280,0x2e00280,0x3400340,0x1c001c0,0x2200220,0x2800280,0x2e002e0,0x2200220,0x2800280,0x2e002e0,0x3400340,
0x400040,0xa000a0,0x1000100,0x1600160,0xa00040,0x1000100,0x1600100,0x1c001c0,0x400040,0xa000a0,0x1000100,0x1600160,0xa000a0,0x1000100,0x1600160,0x1c001c0,
0x30003000,0x30003000,0x30003000,0x30003000,0x30003000,0x30003000,0x30003000,0x30003000,0x0,0x0,0x0,0x0,0x0,0x0,0x0,0x0,
0x30003000,0x30003000,0x30003000,0x30003000,0x30003000,0x30003000,0x30003000,0x30003000,0x0,0x0,0x0,0x0,0x0,0x0,0x0,0x0,
0x2a1f2da8,0xaf64ada8,0xaa1fada8,0x2f642da8,0x2f643000,0xaa1f0000,0xaf64b000,0x2a1f8000,0x2f642da8,0x2a1f2da8,0xaf64ada8,0xaa1fada8,0x2a1f0000,0x2f643000,0xaa1f0000,0xaf64b000,
0x263e2c72,0xafd9aea7,0xa63eac72,0x2fd92ea7,0x2ea72fd9,0xac72a63e,0xaea7afd9,0x2c72263e,0x2fd92ea7,0x263e2c72,0xafd9aea7,0xa63eac72,0x2c72263e,0x2ea72fd9,0xac72a63e,0xaea7afd9,
0x2da80000,0xada80000,0x2da88000,0xada80000,0x2da83000,0xada8b000,0x2da83000,0xada8b000,0x2da83000,0xada8b000,0x2da83000,0xada8b000,0xada80000,0x2da88000,0xada80000,0x2da88000,
0x2f642a1f,0xaf64aa1f,0x2f642a1f,0xaf64aa1f,0x2a1f2f64,0xaa1faf64,0x2a1f2f64,0xaa1faf64,0x2a1f2f64,0xaa1faf64,0x2a1f2f64,0xaa1faf64,0xaf64aa1f,0x2f642a1f,0xaf64aa1f,0x2f642a1f,
0xaa1f2da8,0x2f642da8,0x2a1fada8,0xaf64ada8,0x2f640000,0xaa1fb000,0xaf640000,0x2a1f3000,0xaf64ada8,0xaa1f2da8,0x2f642da8,0x2a1fada8,0x2a1f3000,0x2f648000,0xaa1fb000,0xaf640000,
0xaea7263e,0x2c722fd9,0x2ea7a63e,0xac72afd9,0x2fd92c72,0x263eaea7,0xafd9ac72,0xa63e2ea7,0xac72afd9,0xaea7263e,0x2c722fd9,0x2ea7a63e,0xa63e2ea7,0x2fd92c72,0x263eaea7,0xafd9ac72,
0xada82da8,0xada82da8,0xada82da8,0xada82da8,0x2da8ada8,0x2da8ada8,0x2da8ada8,0x2da8ada8,0x2da82da8,0x2da82da8,0x2da82da8,0x2da82da8,0xada8ada8,0xada8ada8,0xada8ada8,0xada8ada8,
0x3000,0x3000,0x3000,0x80003000,0x8000b000,0x8000b000,0x8000b000,0x8000b000,0x30000000,0x30008000,0x30008000,0x30008000,0xb0000000,0xb0000000,0xb0000000,0xb0000000,
0x2ea7263e,0xac722fd9,0xaea7a63e,0x2c72afd9,0xafd92c72,0xa63eaea7,0x2fd9ac72,0x263e2ea7,0x2c72afd9,0x2ea7263e,0xac722fd9,0xaea7a63e,0x263e2ea7,0xafd92c72,0xa63eaea7,0x2fd9ac72,
0x2f64ada8,0x2a1f2da8,0xaf642da8,0xaa1fada8,0xaa1f3000,0xaf640000,0x2a1fb000,0x2f648000,0xaa1fada8,0x2f64ada8,0x2a1f2da8,0xaf642da8,0x2f640000,0xaa1f3000,0xaf640000,0x2a1fb000,
0xaa1f2f64,0x2a1faf64,0xaa1f2f64,0x2a1faf64,0x2f64aa1f,0xaf642a1f,0x2f64aa1f,0xaf642a1f,0xaf642a1f,0x2f64aa1f,0xaf642a1f,0x2f64aa1f,0xaa1f2f64,0x2a1faf64,0xaa1f2f64,0x2a1faf64,
0x2da80000,0xada80000,0x2da88000,0xada80000,0x2da8b000,0xada83000,0x2da8b000,0xada83000,0xada83000,0x2da8b000,0xada83000,0x2da8b000,0x2da88000,0xada80000,0x2da88000,0xada88000,
0xa63e2c72,0x2fd9aea7,0x263eac72,0xafd92ea7,0xaea72fd9,0x2c72a63e,0x2ea7afd9,0xac72263e,0xafd92ea7,0xa63e2c72,0x2fd9aea7,0x263eac72,0xac72263e,0xaea72fd9,0x2c72a63e,0x2ea7afd9,
0x2f64ada8,0x2a1fada8,0xaf642da8,0xaa1f2da8,0x2a1f0000,0x2f64b000,0xaa1f0000,0xaf643000,0xaa1f2da8,0x2f64ada8,0x2a1fada8,0xaf642da8,0xaf643000,0x2a1f8000,0x2f64b000,0xaa1f8000,
0xb0003000,0xb0003000,0xb0003000,0xb0003000,0xb0003000,0xb0003000,0xb0003000,0xb0003000,0x0,0x8000,0x8000,0x80008000,0x8000,0x8000,0x8000,0x8000,
0x80000000,0x80000000,0x80008000,0x80008000,0x80000000,0x80008000,0x80008000,0x80008000,0xb0003000,0xb0003000,0xb0003000,0xb0003000,0xb0003000,0xb0003000,0xb0003000,0xb0003000,
0xaa1f2da8,0x2f64ada8,0x2a1fada8,0xaf642da8,0xaf643000,0x2a1f0000,0x2f64b000,0xaa1f8000,0xaf642da8,0xaa1f2da8,0x2f64ada8,0x2a1fada8,0xaa1f0000,0xaf643000,0x2a1f0000,0x2f64b000,
0x2fd9aea7,0x263eac72,0xafd92ea7,0xa63e2c72,0x2c72a63e,0x2ea7afd9,0xac72263e,0xaea72fd9,0xa63e2c72,0x2fd9aea7,0x263eac72,0xafd92ea7,0xaea72fd9,0x2c72a63e,0x2ea7afd9,0xac72263e,
0xada80000,0x2da80000,0xada88000,0x2da80000,0xada83000,0x2da8b000,0xada83000,0x2da8b000,0xada83000,0x2da8b000,0xada83000,0x2da8b000,0x2da80000,0xada88000,0x2da88000,0xada88000,
0xaa1f2f64,0x2a1faf64,0xaa1f2f64,0x2a1faf64,0x2f64aa1f,0xaf642a1f,0x2f64aa1f,0xaf642a1f,0x2f64aa1f,0xaf642a1f,0x2f64aa1f,0xaf642a1f,0x2a1faf64,0xaa1f2f64,0x2a1faf64,0xaa1f2f64,
0x2a1f2da8,0xaf642da8,0xaa1fada8,0x2f64ada8,0xaf640000,0x2a1fb000,0x2f640000,0xaa1f3000,0x2f64ada8,0x2a1f2da8,0xaf642da8,0xaa1fada8,0xaa1f3000,0xaf648000,0x2a1fb000,0x2f640000,
0x2c72afd9,0x2ea7263e,0xac722fd9,0xaea7a63e,0x263e2ea7,0xafd92c72,0xa63eaea7,0x2fd9ac72,0xaea7a63e,0x2c72afd9,0x2ea7263e,0xac722fd9,0x2fd9ac72,0x263e2ea7,0xafd92c72,0xa63eaea7,
0x2da8ada8,0x2da8ada8,0x2da8ada8,0x2da8ada8,0xada82da8,0xada82da8,0xada82da8,0xada82da8,0x2da82da8,0x2da82da8,0x2da82da8,0x2da82da8,0xada8ada8,0xada8ada8,0xada8ada8,0xada8ada8,
0x80003000,0x80003000,0x80003000,0x3000,0xb000,0x8000b000,0xb000,0xb000,0xb0000000,0xb0008000,0xb0008000,0xb0008000,0x30000000,0x30000000,0x30000000,0x30008000,
0x2c722fd9,0x2ea7a63e,0xac72afd9,0xaea7263e,0x263eaea7,0xafd9ac72,0xa63e2ea7,0x2fd92c72,0xaea7263e,0x2c722fd9,0x2ea7a63e,0xac72afd9,0x2fd92c72,0x263eaea7,0xafd9ac72,0xa63e2ea7,
0xaf64ada8,0xaa1f2da8,0x2f642da8,0x2a1fada8,0x2a1f3000,0x2f648000,0xaa1fb000,0xaf648000,0x2a1fada8,0xaf64ada8,0xaa1f2da8,0x2f642da8,0xaf640000,0x2a1f3000,0x2f648000,0xaa1fb000,
0x2f642a1f,0xaf64aa1f,0x2f642a1f,0xaf64aa1f,0x2a1f2f64,0xaa1faf64,0x2a1f2f64,0xaa1faf64,0xaa1faf64,0x2a1f2f64,0xaa1faf64,0x2a1f2f64,0x2f642a1f,0xaf64aa1f,0x2f642a1f,0xaf64aa1f,
0xada80000,0x2da80000,0xada88000,0x2da88000,0xada8b000,0x2da83000,0xada8b000,0x2da83000,0x2da83000,0xada8b000,0x2da83000,0xada8b000,0xada88000,0x2da88000,0xada88000,0x2da80000,
0x2fd92ea7,0x263e2c72,0xafd9aea7,0xa63eac72,0x2c72263e,0x2ea72fd9,0xac72a63e,0xaea7afd9,0xa63eac72,0x2fd92ea7,0x263e2c72,0xafd9aea7,0xaea7afd9,0x2c72263e,0x2ea72fd9,0xac72a63e,
0xaf64ada8,0xaa1fada8,0x2f642da8,0x2a1f2da8,0xaa1f0000,0xaf64b000,0x2a1f0000,0x2f643000,0x2a1f2da8,0xaf64ada8,0xaa1fada8,0x2f642da8,0x2f643000,0xaa1f8000,0xaf64b000,0x2a1f0000,
0x80008000,0x80008000,0x80008000,0x80008000,0x80008000,0x80008000,0x80008000,0x80008000,0x30003000,0x30003000,0x30003000,0x30003000,0x30003000,0x30003000,0x30003000,0x30003000,
0x80008000,0x80008000,0x80008000,0x80008000,0x80008000,0x80008000,0x80008000,0x80008000,0x30003000,0x30003000,0x30003000,0x30003000,0x30003000,0x30003000,0x30003000,0x30003000,
0xaf64ada8,0xaa1fada8,0x2f642da8,0x2a1f2da8,0xaa1f8000,0xaf64b000,0x2a1f8000,0x2f643000,0x2a1f2da8,0xaf64ada8,0xaa1fada8,0x2f642da8,0x2f643000,0xaa1f0000,0xaf64b000,0x2a1f8000,
0xafd9aea7,0xa63eac72,0x2fd92ea7,0x263e2c72,0xac72a63e,0xaea7afd9,0x2c72263e,0x2ea72fd9,0x263e2c72,0xafd9aea7,0xa63eac72,0x2fd92ea7,0x2ea72fd9,0xac72a63e,0xaea7afd9,0x2c72263e,
0x2da83000,0xada8b000,0x2da83000,0xada8b000,0xada80000,0x2da88000,0xada80000,0x2da88000,0xada88000,0x2da88000,0xada80000,0x2da88000,0xada8b000,0x2da83000,0xada8b000,0x2da83000,
0x2a1f2f64,0xaa1faf64,0x2a1f2f64,0xaa1faf64,0xaf64aa1f,0x2f642a1f,0xaf64aa1f,0x2f642a1f,0xaf64aa1f,0x2f642a1f,0xaf64aa1f,0x2f642a1f,0xaa1faf64,0x2a1f2f64,0xaa1faf64,0x2a1f2f64,
0xaf64ada8,0xaa1f2da8,0x2f642da8,0x2a1fada8,0x2a1f3000,0x2f648000,0xaa1fb000,0xaf640000,0x2a1fada8,0xaf64ada8,0xaa1f2da8,0x2f642da8,0xaf648000,0x2a1f3000,0x2f648000,0xaa1fb000,
0xac72afd9,0xaea7263e,0x2c722fd9,0x2ea7a63e,0xa63e2ea7,0x2fd92c72,0x263eaea7,0xafd9ac72,0x2ea7a63e,0xac72afd9,0xaea7263e,0x2c722fd9,0xafd9ac72,0xa63e2ea7,0x2fd92c72,0x263eaea7,
0xada8ada8,0xada8ada8,0xada8ada8,0xada8ada8,0x2da82da8,0x2da82da8,0x2da82da8,0x2da82da8,0xada82da8,0xada82da8,0xada82da8,0xada82da8,0x2da8ada8,0x2da8ada8,0x2da8ada8,0x2da8ada8,
0xb0008000,0xb0000000,0xb0000000,0xb0000000,0x30008000,0x30008000,0x30008000,0x30008000,0x3000,0x3000,0x3000,0x80003000,0x8000b000,0x8000b000,0x8000b000,0x8000b000,
0xac722fd9,0xaea7a63e,0x2c72afd9,0x2ea7263e,0xa63eaea7,0x2fd9ac72,0x263e2ea7,0xafd92c72,0x2ea7263e,0xac722fd9,0xaea7a63e,0x2c72afd9,0xafd92c72,0xa63eaea7,0x2fd9ac72,0x263e2ea7,
0x2a1f2da8,0xaf642da8,0xaa1fada8,0x2f64ada8,0xaf648000,0x2a1fb000,0x2f648000,0xaa1f3000,0x2f64ada8,0x2a1f2da8,0xaf642da8,0xaa1fada8,0xaa1f3000,0xaf640000,0x2a1fb000,0x2f648000,
0xaf642a1f,0x2f64aa1f,0xaf642a1f,0x2f64aa1f,0xaa1f2f64,0x2a1faf64,0xaa1f2f64,0x2a1faf64,0x2a1faf64,0xaa1f2f64,0x2a1faf64,0xaa1f2f64,0xaf642a1f,0x2f64aa1f,0xaf642a1f,0x2f64aa1f,
0xada83000,0x2da8b000,0xada83000,0x2da8b000,0x2da88000,0xada80000,0x2da88000,0xada88000,0xada88000,0x2da88000,0xada80000,0x2da88000,0xada83000,0x2da8b000,0xada83000,0x2da8b000,
0xafd92ea7,0xa63e2c72,0x2fd9aea7,0x263eac72,0xac72263e,0xaea72fd9,0x2c72a63e,0x2ea7afd9,0x263eac72,0xafd92ea7,0xa63e2c72,0x2fd9aea7,0x2ea7afd9,0xac72263e,0xaea72fd9,0x2c72a63e,
0xaa1f2da8,0x2f64ada8,0x2a1fada8,0xaf642da8,0xaf643000,0x2a1f8000,0x2f64b000,0xaa1f8000,0xaf642da8,0xaa1f2da8,0x2f64ada8,0x2a1fada8,0xaa1f8000,0xaf643000,0x2a1f8000,0x2f64b000,
0x80008000,0x80000000,0x80000000,0x0,0x80000000,0x80000000,0x80000000,0x80000000,0xb0003000,0xb0003000,0xb0003000,0xb0003000,0xb0003000,0xb0003000,0xb0003000,0xb0003000,
0x3000b000,0x3000b000,0x3000b000,0x3000b000,0x3000b000,0x3000b000,0x3000b000,0x3000b000,0x80000000,0x80000000,0x80008000,0x80008000,0x80000000,0x80008000,0x80008000,0x80008000,
0x2f64ada8,0x2a1fada8,0xaf642da8,0xaa1f2da8,0x2a1f8000,0x2f64b000,0xaa1f8000,0xaf643000,0xaa1f2da8,0x2f64ada8,0x2a1fada8,0xaf642da8,0xaf643000,0x2a1f0000,0x2f64b000,0xaa1f8000,
0x263eac72,0xafd92ea7,0xa63e2c72,0x2fd9aea7,0x2ea7afd9,0xac72263e,0xaea72fd9,0x2c72a63e,0x2fd9aea7,0x263eac72,0xafd92ea7,0xa63e2c72,0x2c72a63e,0x2ea7afd9,0xac72263e,0xaea72fd9,
0xada83000,0x2da8b000,0xada83000,0x2da8b000,0x2da80000,0xada88000,0x2da88000,0xada88000,0x2da88000,0xada88000,0x2da80000,0xada88000,0x2da8b000,0xada83000,0x2da8b000,0xada83000,
0x2f64aa1f,0xaf642a1f,0x2f64aa1f,0xaf642a1f,0x2a1faf64,0xaa1f2f64,0x2a1faf64,0xaa1f2f64,0x2a1faf64,0xaa1f2f64,0x2a1faf64,0xaa1f2f64,0xaf642a1f,0x2f64aa1f,0xaf642a1f,0x2f64aa1f,
0x2f64ada8,0x2a1f2da8,0xaf642da8,0xaa1fada8,0xaa1f3000,0xaf648000,0x2a1fb000,0x2f640000,0xaa1fada8,0x2f64ada8,0x2a1f2da8,0xaf642da8,0x2f648000,0xaa1f3000,0xaf648000,0x2a1fb000,
0xaea7a63e,0x2c72afd9,0x2ea7263e,0xac722fd9,0x2fd9ac72,0x263e2ea7,0xafd92c72,0xa63eaea7,0xac722fd9,0xaea7a63e,0x2c72afd9,0x2ea7263e,0xa63eaea7,0x2fd9ac72,0x263e2ea7,0xafd92c72,
0xada8ada8,0xada8ada8,0xada8ada8,0xada8ada8,0x2da82da8,0x2da82da8,0x2da82da8,0x2da82da8,0x2da8ada8,0x2da8ada8,0x2da8ada8,0x2da8ada8,0xada82da8,0xada82da8,0xada82da8,0xada82da8,
0x30008000,0x30000000,0x30000000,0x30000000,0xb0008000,0xb0008000,0xb0008000,0xb0000000,0x80003000,0x80003000,0x80003000,0x3000,0xb000,0x8000b000,0xb000,0xb000,
0x2ea7a63e,0xac72afd9,0xaea7263e,0x2c722fd9,0xafd9ac72,0xa63e2ea7,0x2fd92c72,0x263eaea7,0x2c722fd9,0x2ea7a63e,0xac72afd9,0xaea7263e,0x263eaea7,0xafd9ac72,0xa63e2ea7,0x2fd92c72,
0xaa1f2da8,0x2f642da8,0x2a1fada8,0xaf64ada8,0x2f648000,0xaa1fb000,0xaf640000,0x2a1f3000,0xaf64ada8,0xaa1f2da8,0x2f642da8,0x2a1fada8,0x2a1f3000,0x2f648000,0xaa1fb000,0xaf648000,
0xaa1faf64,0x2a1f2f64,0xaa1faf64,0x2a1f2f64,0x2f642a1f,0xaf64aa1f,0x2f642a1f,0xaf64aa1f,0xaf64aa1f,0x2f642a1f,0xaf64aa1f,0x2f642a1f,0xaa1faf64,0x2a1f2f64,0xaa1faf64,0x2a1f2f64,
0x2da83000,0xada8b000,0x2da83000,0xada8b000,0xada88000,0x2da88000,0xada88000,0x2da80000,0x2da88000,0xada88000,0x2da80000,0xada80000,0x2da83000,0xada8b000,0x2da83000,0xada8b000,
0xa63eac72,0x2fd92ea7,0x263e2c72,0xafd9aea7,0xaea7afd9,0x2c72263e,0x2ea72fd9,0xac72a63e,0xafd9aea7,0xa63eac72,0x2fd92ea7,0x263e2c72,0xac72a63e,0xaea7afd9,0x2c72263e,0x2ea72fd9,
0x2a1f2da8,0xaf64ada8,0xaa1fada8,0x2f642da8,0x2f643000,0xaa1f8000,0xaf64b000,0x2a1f0000,0x2f642da8,0x2a1f2da8,0xaf64ada8,0xaa1fada8,0x2a1f8000,0x2f643000,0xaa1f8000,0xaf64b000,
0x3c003c00,0x3c003c00,0x3c003c00,0x3c003c00,0x3c003c00,0x3c003c00,0x3c003c00,0x3c003c00,0x80008000,0x80008000,0x80008000,0x80008000,0x80008000,0x80008000,0x80008000,0x80008000,
0x3bd93c00,0x3aa73b64,0x387239a8,0x323e361f,0xb23e0000,0xb872b61f,0xbaa7b9a8,0xbbd9bb64,0xb23e8000,0xb872b61f,0xbaa7b9a8,0xbbd9bb64,0xbbd9bc00,0xbaa7bb64,0xb872b9a8,0xb23eb61f,
0xbb64bc00,0xb61fb9a8,0x361f8000,0x3b6439a8,0x3b643c00,0x361f39a8,0xb61f0000,0xbb64b9a8,0x361f8000,0x3b6439a8,0x3b643c00,0x361f39a8,0xb61f8000,0xbb64b9a8,0xbb64bc00,0xb61fb9a8,
0x38728000,0x3bd93b64,0x323e39a8,0xbaa7b61f,0x3aa73c00,0xb23e361f,0xbbd9b9a8,0xb872bb64,0x3aa73c00,0xb23e361f,0xbbd9b9a8,0xb872bb64,0xb8728000,0xbbd9bb64,0xb23eb9a8,0x3aa7361f,
0xbc008000,0x3c008000,0xbc000000,0x3c008000,0xbc000000,0x3c008000,0xbc000000,0x3c008000,0x3c00,0x8000bc00,0x3c00,0x8000bc00,0x3c00,0x8000bc00,0x80003c00,0x8000bc00,
0xbbd98000,0x3aa7361f,0xb872b9a8,0x323e3b64,0x323ebc00,0xb8723b64,0x3aa7b9a8,0xbbd9361f,0xb23e3c00,0x3872bb64,0xbaa739a8,0x3bd9b61f,0xbbd90000,0x3aa7361f,0xb872b9a8,0x323e3b64,
0x3b648000,0xb61fb9a8,0xb61f3c00,0x3b64b9a8,0xbb648000,0x361f39a8,0x361fbc00,0xbb6439a8,0x361fbc00,0xbb6439a8,0x3b648000,0xb61fb9a8,0xb61f3c00,0x3b64b9a8,0xbb640000,0x361f39a8,
0xb8723c00,0x3bd9b61f,0xb23eb9a8,0xbaa73b64,0xbaa78000,0xb23e3b64,0x3bd9b9a8,0xb872b61f,0x3aa78000,0x323ebb64,0xbbd939a8,0x3872361f,0xb8723c00,0x3bd9b61f,0xb23eb9a8,0xbaa73b64,
0xbbd93c00,0xbaa73b64,0xb87239a8,0xb23e361f,0x323e8000,0x3872b61f,0x3aa7b9a8,0x3bd9bb64,0x323e8000,0x3872b61f,0x3aa7b9a8,0x3bd9bb64,0x3bd9bc00,0x3aa7bb64,0x3872b9a8,0x323eb61f,
0xbc003c00,0xbc003c00,0xbc003c00,0xbc003c00,0xbc003c00,0xbc003c00,0xbc003c00,0xbc003c00,0x80008000,0x80000000,0x80000000,0x80000000,0x80000000,0x80000000,0x0,0x80000000,
0xb8728000,0xbbd93b64,0xb23e39a8,0x3aa7b61f,0xbaa73c00,0x323e361f,0x3bd9b9a8,0x3872bb64,0xbaa73c00,0x323e361f,0x3bd9b9a8,0x3872bb64,0x38728000,0x3bd9bb64,0x323eb9a8,0xbaa7361f,
0x3b64bc00,0x361fb9a8,0xb61f8000,0xbb6439a8,0xbb643c00,0xb61f39a8,0x361f0000,0x3b64b9a8,0xb61f8000,0xbb6439a8,0xbb643c00,0xb61f39a8,0x361f8000,0x3b64b9a8,0x3b64bc00,0x361fb9a8,
0x3bd98000,0xbaa7361f,0x3872b9a8,0xb23e3b64,0xb23ebc00,0x38723b64,0xbaa7b9a8,0x3bd9361f,0x323e3c00,0xb872bb64,0x3aa739a8,0xbbd9b61f,0x3bd98000,0xbaa7361f,0x3872b9a8,0xb23e3b64,
0x3c008000,0xbc008000,0x3c000000,0xbc008000,0x3c000000,0xbc008000,0x3c000000,0xbc000000,0x80003c00,0xbc00,0x80003c00,0x8000bc00,0x80003c00,0xbc00,0x80003c00,0xbc00,
0x38723c00,0xbbd9b61f,0x323eb9a8,0x3aa73b64,0x3aa78000,0x323e3b64,0xbbd9b9a8,0x3872b61f,0xbaa78000,0xb23ebb64,0x3bd939a8,0xb872361f,0x38723c00,0xbbd9b61f,0x323eb9a8,0x3aa73b64,
0xbb640000,0x361fb9a8,0x361f3c00,0xbb64b9a8,0x3b648000,0xb61f39a8,0xb61fbc00,0x3b6439a8,0xb61fbc00,0x3b6439a8,0xbb640000,0x361fb9a8,0x361f3c00,0xbb64b9a8,0x3b648000,0xb61f39a8,
0x39a83c00,0xb9a80000,0xb9a8bc00,0x39a88000,0x39a83c00,0xb9a80000,0xb9a8bc00,0x39a88000,0xb9a88000,0xb9a8bc00,0x39a88000,0x39a83c00,0xb9a80000,0xb9a8bc00,0x39a88000,0x39a83c00,
0x38723c00,0xbbd9b61f,0x323eb9a8,0x3aa73b64,0xbaa70000,0xb23ebb64,0x3bd939a8,0xb872361f,0xbaa78000,0xb23ebb64,0x3bd939a8,0xb872361f,0xb872bc00,0x3bd9361f,0xb23e39a8,0xbaa7bb64,
0xb61fbc00,0x3b6439a8,0xbb640000,0x361fb9a8,0x361f3c00,0xbb64b9a8,0x3b648000,0xb61f39a8,0x3b648000,0xb61f39a8,0xb61fbc00,0x3b6439a8,0xbb648000,0x361fb9a8,0x361f3c00,0xbb64b9a8,
0x3bd98000,0xbaa7361f,0x3872b9a8,0xb23e3b64,0x323e3c00,0xb872bb64,0x3aa739a8,0xbbd9b61f,0x323e3c00,0xb872bb64,0x3aa739a8,0xbbd9b61f,0xbbd98000,0x3aa7b61f,0xb87239a8,0x323ebb64,
0xb9a88000,0xb9a83c00,0x39a88000,0x39a8bc00,0xb9a80000,0xb9a83c00,0x39a88000,0x39a8bc00,0xb9a83c00,0x39a88000,0x39a8bc00,0xb9a80000,0xb9a83c00,0x39a88000,0x39a8bc00,0xb9a88000,
0xb8728000,0xbbd93b64,0xb23e39a8,0x3aa7b61f,0x3aa7bc00,0xb23eb61f,0xbbd939a8,0xb8723b64,0xbaa73c00,0x323e361f,0x3bd9b9a8,0x3872bb64,0xb8728000,0xbbd93b64,0xb23e39a8,0x3aa7b61f,
0x361f8000,0x3b64b9a8,0x3b64bc00,0x361fb9a8,0xb61f8000,0xbb6439a8,0xbb643c00,0xb61f39a8,0x3b64bc00,0x361fb9a8,0xb61f8000,0xbb6439a8,0xbb643c00,0xb61f39a8,0x361f8000,0x3b64b9a8,
0xbbd93c00,0xbaa73b64,0xb87239a8,0xb23e361f,0xb23e8000,0xb872361f,0xbaa739a8,0xbbd93b64,0x323e8000,0x3872b61f,0x3aa7b9a8,0x3bd9bb64,0xbbd93c00,0xbaa73b64,0xb87239a8,0xb23e361f,
0xb8723c00,0x3bd9b61f,0xb23eb9a8,0xbaa73b64,0x3aa78000,0x323ebb64,0xbbd939a8,0x3872361f,0x3aa78000,0x323ebb64,0xbbd939a8,0x3872361f,0x3872bc00,0xbbd9361f,0x323e39a8,0x3aa7bb64,
0xb9a83c00,0x39a80000,0x39a8bc00,0xb9a88000,0xb9a83c00,0x39a88000,0x39a8bc00,0xb9a88000,0x39a88000,0x39a8bc00,0xb9a88000,0xb9a83c00,0x39a80000,0x39a8bc00,0xb9a88000,0xb9a83c00,
0xbbd98000,0x3aa7361f,0xb872b9a8,0x323e3b64,0xb23e3c00,0x3872bb64,0xbaa739a8,0x3bd9b61f,0xb23e3c00,0x3872bb64,0xbaa739a8,0x3bd9b61f,0x3bd98000,0xbaa7b61f,0x387239a8,0xb23ebb64,
0x361fbc00,0xbb6439a8,0x3b640000,0xb61fb9a8,0xb61f3c00,0x3b64b9a8,0xbb648000,0x361f39a8,0xbb648000,0x361f39a8,0x361fbc00,0xbb6439a8,0x3b648000,0xb61fb9a8,0xb61f3c00,0x3b64b9a8,
0x38728000,0x3bd93b64,0x323e39a8,0xbaa7b61f,0xbaa7bc00,0x323eb61f,0x3bd939a8,0x38723b64,0x3aa73c00,0xb23e361f,0xbbd9b9a8,0xb872bb64,0x38728000,0x3bd93b64,0x323e39a8,0xbaa7b61f,
0x39a88000,0x39a83c00,0xb9a88000,0xb9a8bc00,0x39a80000,0x39a83c00,0xb9a80000,0xb9a8bc00,0x39a83c00,0xb9a88000,0xb9a8bc00,0x39a88000,0x39a83c00,0xb9a88000,0xb9a8bc00,0x39a80000,
0x3bd93c00,0x3aa73b64,0x387239a8,0x323e361f,0x323e8000,0x3872361f,0x3aa739a8,0x3bd93b64,0xb23e8000,0xb872b61f,0xbaa7b9a8,0xbbd9bb64,0x3bd93c00,0x3aa73b64,0x387239a8,0x323e361f,
0xb61f8000,0xbb64b9a8,0xbb64bc00,0xb61fb9a8,0x361f8000,0x3b6439a8,0x3b643c00,0x361f39a8,0xbb64bc00,0xb61fb9a8,0x361f0000,0x3b6439a8,0x3b643c00,0x361f39a8,0xb61f8000,0xbb64b9a8,
0x0,0x0,0x0,0x0,0x0,0x0,0x0,0x0,0x3c003c00,0x3c003c00,0x3c003c00,0x3c003c00,0x3c003c00,0x3c003c00,0x3c003c00,0x3c003c00,
0x323e0000,0x3872361f,0x3aa739a8,0x3bd93b64,0x3bd93c00,0x3aa73b64,0x387239a8,0x323e361f,0x3bd93c00,0x3aa73b64,0x387239a8,0x323e361f,0xb23e0000,0xb872b61f,0xbaa7b9a8,0xbbd9bb64,
0xb61f0000,0xbb64b9a8,0xbb64bc00,0xb61fb9a8,0x361f0000,0x3b6439a8,0x3b643c00,0x361f39a8,0xbb64bc00,0xb61fb9a8,0x361f8000,0x3b6439a8,0x3b643c00,0x361f39a8,0xb61f0000,0xbb64b9a8,
0xbaa7bc00,0x323eb61f,0x3bd939a8,0x38723b64,0x38720000,0x3bd93b64,0x323e39a8,0xbaa7b61f,0x38728000,0x3bd93b64,0x323e39a8,0xbaa7b61f,0x3aa73c00,0xb23e361f,0xbbd9b9a8,0xb872bb64,
0x3c00,0x8000bc00,0x3c00,0x8000bc00,0x3c00,0x8000bc00,0x80003c00,0x8000bc00,0x3c000000,0xbc000000,0x3c008000,0xbc000000,0x3c008000,0xbc000000,0x3c008000,0xbc000000,
0xb23e3c00,0x3872bb64,0xbaa739a8,0x3bd9b61f,0xbbd90000,0x3aa7361f,0xb872b9a8,0x323e3b64,0x3bd90000,0xbaa7b61f,0x387239a8,0xb23ebb64,0xb23e3c00,0x3872bb64,0xbaa739a8,0x3bd9b61f,
0x361fbc00,0xbb6439a8,0x3b648000,0xb61fb9a8,0xb61f3c00,0x3b64b9a8,0xbb640000,0x361f39a8,0xbb640000,0x361f39a8,0x361fbc00,0xbb6439a8,0x3b640000,0xb61fb9a8,0xb61f3c00,0x3b64b9a8,
0x3aa78000,0x323ebb64,0xbbd939a8,0x3872361f,0xb8723c00,0x3bd9b61f,0xb23eb9a8,0xbaa73b64,0x3872bc00,0xbbd9361f,0x323e39a8,0x3aa7bb64,0x3aa70000,0x323ebb64,0xbbd939a8,0x3872361f,
0xb23e0000,0xb872361f,0xbaa739a8,0xbbd93b64,0xbbd93c00,0xbaa73b64,0xb87239a8,0xb23e361f,0xbbd93c00,0xbaa73b64,0xb87239a8,0xb23e361f,0x323e8000,0x3872b61f,0x3aa7b9a8,0x3bd9bb64,
0x0,0x8000,0x8000,0x8000,0x8000,0x8000,0x80008000,0x8000,0xbc003c00,0xbc003c00,0xbc003c00,0xbc003c00,0xbc003c00,0xbc003c00,0xbc003c00,0xbc003c00,
0x3aa7bc00,0xb23eb61f,0xbbd939a8,0xb8723b64,0xb8720000,0xbbd93b64,0xb23e39a8,0x3aa7b61f,0xb8728000,0xbbd93b64,0xb23e39a8,0x3aa7b61f,0xbaa73c00,0x323e361f,0x3bd9b9a8,0x3872bb64,
0x361f0000,0x3b64b9a8,0x3b64bc00,0x361fb9a8,0xb61f0000,0xbb6439a8,0xbb643c00,0xb61f39a8,0x3b64bc00,0x361fb9a8,0xb61f8000,0xbb6439a8,0xbb643c00,0xb61f39a8,0x361f0000,0x3b64b9a8,
0x323e3c00,0xb872bb64,0x3aa739a8,0xbbd9b61f,0x3bd98000,0xbaa7361f,0x3872b9a8,0xb23e3b64,0xbbd90000,0x3aa7b61f,0xb87239a8,0x323ebb64,0x323e3c00,0xb872bb64,0x3aa739a8,0xbbd9b61f,
0x80003c00,0xbc00,0x80003c00,0x8000bc00,0x80003c00,0xbc00,0x80003c00,0xbc00,0xbc000000,0x3c000000,0xbc008000,0x3c000000,0xbc008000,0x3c000000,0xbc008000,0x3c008000,
0xbaa78000,0xb23ebb64,0x3bd939a8,0xb872361f,0x38723c00,0xbbd9b61f,0x323eb9a8,0x3aa73b64,0xb872bc00,0x3bd9361f,0xb23e39a8,0xbaa7bb64,0xbaa70000,0xb23ebb64,0x3bd939a8,0xb872361f,
0xb61fbc00,0x3b6439a8,0xbb640000,0x361fb9a8,0x361f3c00,0xbb64b9a8,0x3b648000,0xb61f39a8,0x3b648000,0xb61f39a8,0xb61fbc00,0x3b6439a8,0xbb640000,0x361fb9a8,0x361f3c00,0xbb64b9a8,
0x39a80000,0x39a83c00,0xb9a80000,0xb9a8bc00,0x39a88000,0x39a83c00,0xb9a80000,0xb9a8bc00,0x39a83c00,0xb9a80000,0xb9a8bc00,0x39a88000,0x39a83c00,0xb9a80000,0xb9a8bc00,0x39a88000,
0x3aa70000,0x323e3b64,0xbbd9b9a8,0x3872b61f,0x38723c00,0xbbd9b61f,0x323eb9a8,0x3aa73b64,0x38723c00,0xbbd9b61f,0x323eb9a8,0x3aa73b64,0xbaa70000,0xb23ebb64,0x3bd939a8,0xb872361f,
0xbb640000,0x361fb9a8,0x361f3c00,0xbb64b9a8,0x3b640000,0xb61f39a8,0xb61fbc00,0x3b6439a8,0xb61fbc00,0x3b6439a8,0xbb640000,0x361fb9a8,0x361f3c00,0xbb64b9a8,0x3b648000,0xb61f39a8,
0xb23ebc00,0x38723b64,0xbaa7b9a8,0x3bd9361f,0x3bd90000,0xbaa7361f,0x3872b9a8,0xb23e3b64,0x3bd98000,0xbaa7361f,0x3872b9a8,0xb23e3b64,0x323e3c00,0xb872bb64,0x3aa739a8,0xbbd9b61f,
0xb9a83c00,0x39a88000,0x39a8bc00,0xb9a80000,0xb9a83c00,0x39a88000,0x39a8bc00,0xb9a88000,0x39a80000,0x39a8bc00,0xb9a80000,0xb9a83c00,0x39a88000,0x39a8bc00,0xb9a80000,0xb9a83c00,
0xbaa73c00,0x323e361f,0x3bd9b9a8,0x3872bb64,0xb8728000,0xbbd93b64,0xb23e39a8,0x3aa7b61f,0x38720000,0x3bd9bb64,0x323eb9a8,0xbaa7361f,0xbaa73c00,0x323e361f,0x3bd9b9a8,0x3872bb64,
0x3b64bc00,0x361fb9a8,0xb61f8000,0xbb6439a8,0xbb643c00,0xb61f39a8,0x361f8000,0x3b64b9a8,0xb61f0000,0xbb6439a8,0xbb643c00,0xb61f39a8,0x361f0000,0x3b64b9a8,0x3b64bc00,0x361fb9a8,
0x323e8000,0x3872b61f,0x3aa7b9a8,0x3bd9bb64,0xbbd93c00,0xbaa73b64,0xb87239a8,0xb23e361f,0x3bd9bc00,0x3aa7bb64,0x3872b9a8,0x323eb61f,0x323e0000,0x3872b61f,0x3aa7b9a8,0x3bd9bb64,
0xbaa70000,0xb23e3b64,0x3bd9b9a8,0xb872b61f,0xb8723c00,0x3bd9b61f,0xb23eb9a8,0xbaa73b64,0xb8723c00,0x3bd9b61f,0xb23eb9a8,0xbaa73b64,0x3aa78000,0x323ebb64,0xbbd939a8,0x3872361f,
0xb9a80000,0xb9a83c00,0x39a80000,0x39a8bc00,0xb9a88000,0xb9a83c00,0x39a80000,0x39a8bc00,0xb9a83c00,0x39a80000,0x39a8bc00,0xb9a88000,0xb9a83c00,0x39a88000,0x39a8bc00,0xb9a88000,
0x323ebc00,0xb8723b64,0x3aa7b9a8,0xbbd9361f,0xbbd90000,0x3aa7361f,0xb872b9a8,0x323e3b64,0xbbd98000,0x3aa7361f,0xb872b9a8,0x323e3b64,0xb23e3c00,0x3872bb64,0xbaa739a8,0x3bd9b61f,
0x3b640000,0xb61fb9a8,0xb61f3c00,0x3b64b9a8,0xbb640000,0x361f39a8,0x361fbc00,0xbb6439a8,0x361fbc00,0xbb6439a8,0x3b640000,0xb61fb9a8,0xb61f3c00,0x3b64b9a8,0xbb648000,0x361f39a8,
0x3aa73c00,0xb23e361f,0xbbd9b9a8,0xb872bb64,0x38728000,0x3bd93b64,0x323e39a8,0xbaa7b61f,0xb8720000,0xbbd9bb64,0xb23eb9a8,0x3aa7361f,0x3aa73c00,0xb23e361f,0xbbd9b9a8,0xb872bb64,
0x39a83c00,0xb9a88000,0xb9a8bc00,0x39a88000,0x39a83c00,0xb9a88000,0xb9a8bc00,0x39a80000,0xb9a80000,0xb9a8bc00,0x39a80000,0x39a83c00,0xb9a88000,0xb9a8bc00,0x39a88000,0x39a83c00,
0xb23e8000,0xb872b61f,0xbaa7b9a8,0xbbd9bb64,0x3bd93c00,0x3aa73b64,0x387239a8,0x323e361f,0xbbd9bc00,0xbaa7bb64,0xb872b9a8,0xb23eb61f,0xb23e0000,0xb872b61f,0xbaa7b9a8,0xbbd9bb64,
0xbb64bc00,0xb61fb9a8,0x361f0000,0x3b6439a8,0x3b643c00,0x361f39a8,0xb61f8000,0xbb64b9a8,0x361f0000,0x3b6439a8,0x3b643c00,0x361f39a8,0xb61f0000,0xbb64b9a8,0xbb64bc00,0xb61fb9a8,
};
__device__ __align__(1024) bf16 g_x1T[DM * XP];
__device__ __align__(1024) bf16 g_x2T[DM * XP];
__device__ __align__(1024) uint32_t g_fin[DM / 2][SEQ];
__device__ __align__(1024) float g_sums[2][2][SEQ];

#define TS_DECL
#define TS_ARG
#define TS_PASS
#define TS_PHASE(p)
#define TS(i)
#define TSX(row, i)
#define TS_BEGIN
#define TS_END

__device__ __align__(1024) uint32_t g_keo[DM / 2][2048];
__device__ __align__(128) uint32_t g_ksc[DM];

struct cplx { float r, i; };
__device__ __forceinline__ cplx cmul(cplx a, cplx b) {
    cplx o;
    o.r = fmaf(a.r, b.r, -a.i * b.i);
    o.i = fmaf(a.r, b.i, a.i * b.r);
    return o;
}
__device__ __forceinline__ cplx csq(cplx a) {
    cplx o;
    o.r = fmaf(a.r, a.r, -a.i * a.i);
    o.i = 2.f * a.r * a.i;
    return o;
}
__device__ __forceinline__ cplx cexp_p(float arl, float ai, float p) {
    float mag = ex2(arl * p);
    float ang = ai * p;
    float n = rintf(ang * 0.15915494309189535f);
    float r = fmaf(n, -6.2831854820251465f, ang);
    r = fmaf(n, 1.7484555e-7f, r);
    cplx o;
    o.r = mag * __cosf(r);
    o.i = mag * __sinf(r);
    return o;
}

__device__ __forceinline__ uint32_t pack2h(float lo, float hi) {
    uint32_t r;
    asm("cvt.rn.f16x2.f32 %0, %1, %2;" : "=r"(r) : "f"(hi), "f"(lo));
    return r;
}
__device__ __forceinline__ uint32_t hmul(uint32_t a, uint32_t b) { uint32_t d; asm("mul.rn.f16x2 %0, %1, %2;" : "=r"(d) : "r"(a), "r"(b)); return d; }
__device__ __forceinline__ uint32_t hfma(uint32_t a, uint32_t b, uint32_t c) { uint32_t d; asm("fma.rn.f16x2 %0, %1, %2, %3;" : "=r"(d) : "r"(a), "r"(b), "r"(c)); return d; }
__device__ __forceinline__ uint32_t hfms(uint32_t a, uint32_t b, uint32_t c) {
    uint32_t d;
    asm("{\n.reg .b32 n;\nneg.f16x2 n, %1;\nfma.rn.f16x2 %0, n, %2, %3;\n}" : "=r"(d) : "r"(a), "r"(b), "r"(c));
    return d;
}
__device__ __forceinline__ uint32_t hadd(uint32_t a, uint32_t b) { uint32_t d; asm("add.rn.f16x2 %0, %1, %2;" : "=r"(d) : "r"(a), "r"(b)); return d; }
__device__ __forceinline__ uint32_t hsub(uint32_t a, uint32_t b) { uint32_t d; asm("sub.rn.f16x2 %0, %1, %2;" : "=r"(d) : "r"(a), "r"(b)); return d; }
__device__ __forceinline__ uint4 ldg_tab(int tab, int t) {
    uint4 v;
    asm volatile("ld.global.nc.v4.u32 {%0,%1,%2,%3}, [%4];" : "=r"(v.x), "=r"(v.y), "=r"(v.z), "=r"(v.w) : "l"((const uint4*)c_fft + tab * 128 + t));
    return v;
}
__device__ __forceinline__ uint32_t u4(const uint4& v, int i) { return i == 0 ? v.x : i == 1 ? v.y : i == 2 ? v.z : v.w; }
struct cpair { uint32_t r, i; };
__device__ __forceinline__ cpair pmul(cpair p, uint32_t z) {
    const __half2 zv = *reinterpret_cast<const __half2*>(&z), pr = *reinterpret_cast<const __half2*>(&p.r), pi = *reinterpret_cast<const __half2*>(&p.i);
    const __half2 zr = __low2half2(zv), zi = __high2half2(zv);
    const __half2 a = __hfma2(__hneg2(pi), zi, __hmul2(pr, zr)), b = __hfma2(pi, zr, __hmul2(pr, zi));
    return {*reinterpret_cast<const uint32_t*>(&a), *reinterpret_cast<const uint32_t*>(&b)};
}
__device__ __forceinline__ uint32_t packz(cplx z) { return pack2h(z.r, z.i); }
__device__ __forceinline__ void wgmma_kg(float (&d)[24], uint64_t da, uint64_t db, int scale_d) {
    asm volatile("{\n.reg .pred p;\nsetp.ne.b32 p, %26, 0;\n"
                 "wgmma.mma_async.sync.aligned.m64n48k16.f32.f16.f16 "
                 "{%0,%1,%2,%3,%4,%5,%6,%7,%8,%9,%10,%11,%12,%13,%14,%15,%16,%17,%18,%19,%20,%21,%22,%23}, %24, %25, p, 1, 1, 1, 1;\n}\n"
                 : "+f"(d[0]), "+f"(d[1]), "+f"(d[2]), "+f"(d[3]), "+f"(d[4]), "+f"(d[5]), "+f"(d[6]), "+f"(d[7]), "+f"(d[8]), "+f"(d[9]),
                   "+f"(d[10]), "+f"(d[11]), "+f"(d[12]), "+f"(d[13]), "+f"(d[14]), "+f"(d[15]), "+f"(d[16]), "+f"(d[17]), "+f"(d[18]), "+f"(d[19]),
                   "+f"(d[20]), "+f"(d[21]), "+f"(d[22]), "+f"(d[23])
                 : "l"(da), "l"(db), "r"(scale_d));
}

struct SsmParams { const bf16 *lar, *aim, *cre, *cim, *logdt, *dskip; };
constexpr int KG_TABLES = 6 * 16384, KG_IDX = 6 * 3072, KG_DUMP = KG_IDX + 4096;
struct KgShared { uint32_t kmax[5]; };
struct KgParams { uint32_t l[3], a[3], r[3], i[3], dt, ds; };

__device__ __forceinline__ void kgen_load(KgParams& kp, int d0, int warp, int lane, const SsmParams& sp) {
    const int d = d0 + (warp < 8 ? 2 * (warp >> 2) + (warp & 1) : 4), idx = d * (NMODE / 2) + lane;
    const bf16 *pr = (warp & 2) ? sp.cre : sp.lar, *pi = (warp & 2) ? sp.cim : sp.aim;
#pragma unroll
    for (int j = 0; j < 3; j++) {
        kp.l[j] = __ldg((const uint32_t*)sp.lar + idx + 32 * j); kp.a[j] = __ldg((const uint32_t*)sp.aim + idx + 32 * j);
        kp.r[j] = __ldg((const uint32_t*)pr + idx + 32 * j); kp.i[j] = __ldg((const uint32_t*)pi + idx + 32 * j);
    }
    kp.dt = __ldg((const uint16_t*)sp.logdt + d);
    kp.ds = __ldg((const uint16_t*)sp.dskip + d0 + min(warp >> 1, 4));
}

struct KgAnchors { uint32_t v[8]; };
__device__ __forceinline__ KgAnchors kg_anchor_lo(const KgParams& kp, uint32_t sel, float dt) {
    auto B = [&](uint32_t v) { return __uint_as_float(__byte_perm(v, 0u, sel)); };
    const float arl = -rbf(ex2(B(kp.l[0]) * 1.4426950408889634f)) * dt * 1.4426950408889634f, ai = B(kp.a[0]) * dt;
    const cplx z8 = cexp_p(arl, ai, 8.f), z16 = csq(z8), z24 = cmul(z16, z8), z32 = csq(z16), z64 = csq(z32), z128 = csq(z64), z192 = cmul(z128, z64);
    return {{pack2h(1.f, z8.r), pack2h(0.f, z8.i), pack2h(z16.r, z24.r), pack2h(z16.i, z24.i), packz(z32), packz(z64), packz(z128), packz(z192)}};
}
__device__ __forceinline__ KgAnchors kg_anchor_hi(const KgParams& kp, uint32_t sel, float dt, float cs) {
    auto B = [&](uint32_t v) { return __uint_as_float(__byte_perm(v, 0u, sel)); };
    const float arl = -rbf(ex2(B(kp.l[0]) * 1.4426950408889634f)) * dt * 1.4426950408889634f, ai = B(kp.a[0]) * dt;
    const cplx z1 = cexp_p(arl, -ai, 1.f), z2 = csq(z1), z4 = csq(z2), z256 = cexp_p(arl, -ai, 256.f), z512 = csq(z256), z1024 = csq(z512);
    const cplx H0 = {B(kp.r[0]) * cs, -B(kp.i[0]) * cs}, H4 = cmul(H0, z4);
    return {{pack2h(H0.r, H4.r), pack2h(H0.i, H4.i), packz(z1), packz(z2), packz(z256), packz(z512), packz(z1024), 0u}};
}

template <class Hook>
__device__ __forceinline__ void kgen_tables(KgParams& kp, uint32_t scr, uint32_t dump, int warp, int lane, Hook hook TS_ARG) {
    const int wg = warp >> 2, half = warp & 1, sw = lane & 7;
    const bool hi = warp & 2;
    TS(23);
    const float dt = rbf(ex2(bf_lo(kp.dt) * 1.4426950408889634f));
    uint32_t sel = (wg == 2 && half) ? 0x3244u : 0x1044u;
    float cs = 0.f;
    KgAnchors an;
    if (hi) {
        uint32_t m = 0;
#pragma unroll
        for (int j = 0; j < 3; j++) m = __vmaxu2(m, __vmaxu2(kp.r[j] & 0x7FFF7FFFu, kp.i[j] & 0x7FFF7FFFu));
        m = __reduce_max_sync(~0u, max(m << 16, m & 0xFFFF0000u));
        const uint32_t e = min(max(__float_as_uint(2.f * dt * __uint_as_float(m)) >> 23, 2u), 252u);
        cs = 2.f * dt * __uint_as_float((253u - e) << 23);
        if (lane == 0) sts32(dump + (2 * wg + half) * 3072, (e + 1u) << 23);
        an = kg_anchor_hi(kp, sel, dt, cs);
    } else {
        an = kg_anchor_lo(kp, sel, dt);
    }
    if (an.v[0] != 0xFFFFFFFFu) hook();
    float acc[24];
    const int nstep = wg == 2 ? 3 : 6;
#pragma unroll 1
    for (int c = 0; c < nstep; c++) {
        if (wg < 2) sel ^= 0x2200u;
        if (wg == 2 || (c & 1)) {
#pragma unroll
            for (int j = 0; j < 2; j++) { kp.l[j] = kp.l[j + 1]; kp.a[j] = kp.a[j + 1]; kp.r[j] = kp.r[j + 1]; kp.i[j] = kp.i[j + 1]; }
        }
        const uint32_t buf = scr + (2 * wg + (c & 1)) * 16384, tb = buf + lane * 128;
        if (!hi) {
            cpair p[4];
            p[0] = {an.v[0], an.v[1]}; p[1] = {an.v[2], an.v[3]};
            p[2] = pmul(p[0], an.v[4]); p[3] = pmul(p[1], an.v[4]);
#pragma unroll
            for (int j = 0; j < 4; j++) {
                cpair v[4];
#pragma unroll
                for (int i = 0; i < 4; i++) v[i] = j ? pmul(p[i], an.v[4 + j]) : p[i];
                const uint32_t a = tb + (((4 * half + j) ^ sw) << 4);
                sts128(a, make_uint4(v[0].r, v[1].r, v[2].r, v[3].r));
                sts128(a + 4096, make_uint4(v[0].i, v[1].i, v[2].i, v[3].i));
            }
            an = kg_anchor_lo(kp, sel, dt);
        } else {
            const uint32_t h1 = an.v[2], h2 = an.v[3], h256 = an.v[4], h512 = an.v[5], h1024 = an.v[6];
            cpair p[11];
            p[0] = {an.v[0], an.v[1]};
            p[1] = pmul(p[0], h2); p[2] = pmul(p[0], h1); p[3] = pmul(p[1], h1);
            p[4] = pmul(p[0], h256); p[5] = pmul(p[1], h256); p[6] = pmul(p[0], h512); p[7] = pmul(p[4], h512);
            p[8] = pmul({__byte_perm(p[0].r, p[4].r, 0x5410), __byte_perm(p[0].i, p[4].i, 0x5410)}, h1024);
            p[9] = pmul(p[8], h512); p[10] = pmul(p[8], h1024);
#pragma unroll
            for (int j = 0; j < 3; j++) {
                const uint32_t a = tb + 8192 + (((3 * half + j) ^ sw) << 4);
                sts128(a, make_uint4(p[4 * j].r, p[4 * j + 1].r, p[4 * j + 2].r, p[j < 2 ? 4 * j + 3 : 10].r));
                sts128(a + 4096, make_uint4(p[4 * j].i, p[4 * j + 1].i, p[4 * j + 2].i, p[j < 2 ? 4 * j + 3 : 10].i));
            }
            an = kg_anchor_hi(kp, sel, dt, cs);
        }
        if (c == 0) TS(24);
        if (c == 2) TS(26);
        fence_async_smem();
        wg_wait<0>();
        named_bar(5 + wg, 128);
        if (c == 1) TS(25);
        if (c == 2) TS(28);
        const uint64_t da = mkdesc(buf, 4096, 1024, 1);
        wg_fence();
#pragma unroll
        for (int k = 0; k < 4; k++) wgmma_kg(acc, da + k * 128, da + 512 + k * 128, k > 0 || c > 0);
        wg_commit();
    }
    const uint32_t ob = dump + (2 * wg + (hi ? 1 : 0)) * 3072, o = ob + ((16 * half + (lane >> 2)) * 24 + 2 * (lane & 3)) * 4;
    const float ci = __uint_as_float(lds32(ob));
    const float ds = (lane == 0 && warp <= 8 && !half) ? bf_lo(kp.ds) : 0.f;
    named_bar(5 + wg, 128);
    wg_wait<0>();
#pragma unroll
    for (int j = 0; j < 3; j++)
#pragma unroll
        for (int h = 0; h < 2; h++)
            asm volatile("st.shared.v2.f32 [%0], {%1, %2};" ::"r"(o + h * 768 + j * 32), "f"(fmaf(ci, hi ? acc[12 + 4 * j + 2 * h] : acc[4 * j + 2 * h], j + h ? 0.f : ds)),
                         "f"(ci * (hi ? acc[13 + 4 * j + 2 * h] : acc[4 * j + 2 * h + 1])) : "memory");
}

__device__ __forceinline__ void kgen_expand(int d0, uint32_t dump, KgShared* ks, int ht TS_ARG) {
    const int lane = ht & 31;
    auto F = [](uint32_t x) { return __uint_as_float(x); };
#pragma unroll 1
    for (int c = 0; c < 5; c++) {
        float m = 0.f;
#pragma unroll
        for (int i = 0; i < 2; i++) {
            const uint32_t a = dump + c * 3072 + (ht + 96 * i) * 16;
            const uint4 x = lds128(a), y = c == 4 ? lds128(a + 3072) : make_uint4(0, 0, 0, 0);
            const float v0 = F(x.x) + F(y.x), v1 = F(x.y) + F(y.y), v2 = F(x.z) + F(y.z), v3 = F(x.w) + F(y.w);
            if (c == 4) sts128(a, make_uint4(__float_as_uint(v0), __float_as_uint(v1), __float_as_uint(v2), __float_as_uint(v3)));
            m = fmaxf(fmaxf(m, fmaxf(fabsf(v0), fabsf(v1))), fmaxf(fabsf(v2), fabsf(v3)));
        }
        const uint32_t mm = __reduce_max_sync(~0u, __float_as_uint(m));
        if (lane == 0) asm volatile("red.shared.max.u32 [%0], %1;" ::"r"(s2u(&ks->kmax[c])), "r"(mm) : "memory");
    }
    named_bar(4, 96);
    TSX(2, 6);
#pragma unroll 1
    for (int task = ht >> 5; task < 20; task += 3) {
        const int c = task >> 2, it = (task & 3) * 32 + lane, a = it >> 2, d = d0 + c;
        const uint4 o0 = lds128(dump + KG_IDX + it * 16), o1 = lds128(dump + KG_IDX + 2048 + it * 16);
        const uint32_t e = min(max(ks->kmax[c] >> 23, 4u), 250u), b = dump + c * 3072;
        const float sc = __uint_as_float((253u - e) << 23);
        if (it == 0) g_ksc[d] = e;
        uint32_t ev[4], ov[4];
#pragma unroll
        for (int i = 0; i < 4; i++) {
            const float x0 = F(lds32(b + (u4(o0, i) & 0xFFFF))), x1 = F(lds32(b + (u4(o0, i) >> 16)));
            const float y0 = F(lds32(b + (u4(o1, i) & 0xFFFF))), y1 = F(lds32(b + (u4(o1, i) >> 16)));
            ev[i] = pack2h((x0 + y0) * sc, (x1 + y1) * sc);
            ov[i] = pack2h((x0 - y0) * sc, (x1 - y1) * sc);
        }
        uint32_t* dst = &g_keo[d >> 1][a * 32 + (((4 * (d & 1) + (it & 3)) ^ (a & 7)) << 2)];
        stg128(dst, make_uint4(ev[0], ev[1], ev[2], ev[3]));
        stg128(dst + 1024, make_uint4(ov[0], ov[1], ov[2], ov[3]));
    }
}
__device__ __forceinline__ void wgmma_h64_rs(uint32_t (&d)[16], const uint4& a, uint64_t db, int scale_d) {
    asm volatile("{\n.reg .pred p;\nsetp.ne.b32 p, %21, 0;\n"
                 "wgmma.mma_async.sync.aligned.m64n64k16.f16.f16.f16 {%0,%1,%2,%3,%4,%5,%6,%7,%8,%9,%10,%11,%12,%13,%14,%15}, {%16,%17,%18,%19}, %20, p, 1, 1, 1;\n}\n"
                 : "+r"(d[0]), "+r"(d[1]), "+r"(d[2]), "+r"(d[3]), "+r"(d[4]), "+r"(d[5]), "+r"(d[6]), "+r"(d[7]), "+r"(d[8]), "+r"(d[9]),
                   "+r"(d[10]), "+r"(d[11]), "+r"(d[12]), "+r"(d[13]), "+r"(d[14]), "+r"(d[15])
                 : "r"(a.x), "r"(a.y), "r"(a.z), "r"(a.w), "l"(db), "r"(scale_d));
}
__device__ __forceinline__ void wgmma_h32_rs(uint32_t (&d)[8], const uint32_t (&a)[4], uint64_t db, int scale_d) {
    asm volatile("{\n.reg .pred p;\nsetp.ne.b32 p, %13, 0;\n"
                 "wgmma.mma_async.sync.aligned.m64n32k16.f16.f16.f16 {%0,%1,%2,%3,%4,%5,%6,%7}, {%8,%9,%10,%11}, %12, p, 1, 1, 0;\n}\n"
                 : "+r"(d[0]), "+r"(d[1]), "+r"(d[2]), "+r"(d[3]), "+r"(d[4]), "+r"(d[5]), "+r"(d[6]), "+r"(d[7])
                 : "r"(a[0]), "r"(a[1]), "r"(a[2]), "r"(a[3]), "l"(db), "r"(scale_d));
}
__device__ __forceinline__ void wgmma_sp64_rs(float (&d)[32], const uint4& a, uint64_t db, uint32_t meta, int scale_d) {
    asm volatile("{\n.reg .pred p;\nsetp.ne.b32 p, %38, 0;\n"
                 "wgmma.mma_async.sp.sync.aligned.m64n64k32.f32.f16.f16 "
                 "{%0,%1,%2,%3,%4,%5,%6,%7,%8,%9,%10,%11,%12,%13,%14,%15,%16,%17,%18,%19,%20,%21,%22,%23,%24,%25,%26,%27,%28,%29,%30,%31}, "
                 "{%32,%33,%34,%35}, %36, %37, 0, p, 1, 1, 1;\n}\n"
                 : "+f"(d[0]), "+f"(d[1]), "+f"(d[2]), "+f"(d[3]), "+f"(d[4]), "+f"(d[5]), "+f"(d[6]), "+f"(d[7]), "+f"(d[8]), "+f"(d[9]),
                   "+f"(d[10]), "+f"(d[11]), "+f"(d[12]), "+f"(d[13]), "+f"(d[14]), "+f"(d[15]), "+f"(d[16]), "+f"(d[17]), "+f"(d[18]), "+f"(d[19]),
                   "+f"(d[20]), "+f"(d[21]), "+f"(d[22]), "+f"(d[23]), "+f"(d[24]), "+f"(d[25]), "+f"(d[26]), "+f"(d[27]), "+f"(d[28]), "+f"(d[29]),
                   "+f"(d[30]), "+f"(d[31])
                 : "r"(a.x), "r"(a.y), "r"(a.z), "r"(a.w), "l"(db), "r"(meta), "r"(scale_d));
}

__device__ __forceinline__ void fft_stage(const uint32_t (&u)[2][2][4], uint32_t eo, int warp4, int lane) {
    const int mi = lane >> 3, mj = lane & 7;
#pragma unroll
    for (int c = 0; c < 2; c++) {
        const uint32_t a = eo + (8 * warp4 + mj) * 128 + (((4 * c + mi) ^ mj) << 4);
        stsm_x4(a, hadd(u[c][0][0], u[c][1][0]), hadd(u[c][0][1], u[c][1][1]), hadd(u[c][0][2], u[c][1][2]), hadd(u[c][0][3], u[c][1][3]));
        stsm_x4(a + 4096, hsub(u[c][0][0], u[c][1][0]), hsub(u[c][0][1], u[c][1][1]), hsub(u[c][0][2], u[c][1][2]), hsub(u[c][0][3], u[c][1][3]));
    }
    fence_async_smem();
}
__device__ __forceinline__ void fft_forward(const uint4 (&a1)[4], const uint4 (&tw)[4], uint32_t eo, uint32_t s2, uint32_t (&X)[2][2][8]) {
    uint32_t dr[16], di[16];
    const uint64_t de = mkdesc(eo, 4096, 1024, 1), d2 = mkdesc(s2, 16, 1024, 1);
    wg_fence();
    wgmma_h64_rs(dr, a1[0], de, 0);
    wgmma_h64_rs(di, a1[2], de + 256, 0);
    wgmma_h64_rs(dr, a1[1], de + 128, 1);
    wgmma_h64_rs(di, a1[3], de + 384, 1);
    wg_commit();
    wg_wait<0>();
#pragma unroll
    for (int c = 0; c < 2; c++) {
        uint32_t zr[2][4], zi[2][4];
#pragma unroll
        for (int p = 0; p < 2; p++)
#pragma unroll
            for (int i = 0; i < 4; i++) {
                const uint32_t r = dr[8 * c + 4 * p + i], m = di[8 * c + 4 * p + i], tr = u4(tw[p], i), ti = u4(tw[2 + p], i);
                zr[p][i] = hfms(m, ti, hmul(r, tr));
                zi[p][i] = hfma(m, tr, hmul(r, ti));
            }
        wg_fence();
        wgmma_h32_rs(X[c][0], zr[0], d2, 0);
        wgmma_h32_rs(X[c][1], zr[1], d2 + 4, 0);
        wgmma_h32_rs(X[c][0], zi[0], d2 + 2, 1);
        wgmma_h32_rs(X[c][1], zi[1], d2 + 6, 1);
        wg_commit();
    }
}

template <class Ready>
__device__ __forceinline__ void conv_pair(int ch0, int layer, uint32_t eo, uint32_t zb, uint32_t s23, uint32_t kbar, int warp, int lane, Ready ready TS_ARG) {
    const int wg = warp >> 2, w = warp & 3, t = 32 * w + lane, g = lane >> 2, q = lane & 3, mi = lane >> 3, mj = lane & 7;
    const bf16* xT = g_x1T;
    const float* sums = g_sums[layer][0];
    uint4 a1[4], tw[4];
#pragma unroll
    for (int i = 0; i < 4; i++) { a1[i] = ldg_tab(i, t); tw[i] = ldg_tab(8 + i, t); }
    uint32_t u[2][2][4], KH[2][2][8];
    TS(1);
    mbar_wait(kbar, 0);
    const uint2 ke = ldg64(g_ksc + ch0);
    TS(2);
    fft_forward(a1, tw, eo, s23, KH);
    named_bar(1 + wg, 128);
#pragma unroll
    for (int i = 0; i < 4; i++) tw[i] = ldg_tab(4 + i, t);
    const uint32_t oscale[2] = {(ke.x + 3u) * 0x00800080u, (ke.y + 3u) * 0x00800080u};
    wg_wait<0>();
    TS(4);
    ready();
    TS(5);
    uint2 x[2][2][2];
    const int ra[2] = {16 * (8 * w + g) + 4 * q, 16 * (63 - 8 * w - g) + 4 * q};
    {
        uint4 s[2][2][2];
#pragma unroll
        for (int h = 0; h < 2; h++)
#pragma unroll
            for (int p = 0; p < 2; p++) {
                s[h][p][0] = ldg128(sums + 1024 * p + ra[h]);
                s[h][p][1] = ldg128(sums + SEQ + 1024 * p + ra[h]);
#pragma unroll
                for (int c = 0; c < 2; c++) x[c][h][p] = ldg64(xT + (size_t)(ch0 + c) * XP + 1024 * p + ra[h]);
            }
        TS(6);
#pragma unroll
        for (int h = 0; h < 2; h++)
#pragma unroll
            for (int j = 0; j < 4; j++) {
                const uint4 sa = s[h][j >> 1][0], sq = s[h][j >> 1][1];
                const float4 v = make_float4(__uint_as_float(u4(sa, 2 * (j & 1))), __uint_as_float(u4(sq, 2 * (j & 1))),
                                             __uint_as_float(u4(sa, 2 * (j & 1) + 1)), __uint_as_float(u4(sq, 2 * (j & 1) + 1)));
                const float m0 = v.x * (1.0f / DM), m1 = v.z * (1.0f / DM);
                const float r0 = frsq(fmaxf(fmaf(v.y, 1.0f / DM, fmaf(-m0, m0, 1e-5f)), 1e-5f));
                const float r1 = frsq(fmaxf(fmaf(v.w, 1.0f / DM, fmaf(-m1, m1, 1e-5f)), 1e-5f));
                const float c0 = -m0 * r0, c1 = -m1 * r1;
#pragma unroll
                for (int c = 0; c < 2; c++) {
                    const uint32_t xv = (j & 1) ? x[c][h][j >> 1].y : x[c][h][j >> 1].x;
                    u[c][h][j] = pack2h(fmaf(bf_lo(xv), r0, c0), fmaf(bf_hi(xv), r1, c1));
                }
            }
    }
    TS(8);
    uint32_t X[2][2][8], Y[2][2][8];
    fft_stage(u, eo, w, lane);
    TS(9);
    named_bar(1 + wg, 128);
    fft_forward(a1, tw, eo, s23, X);
    TS(10);
#pragma unroll
    for (int i = 0; i < 4; i++) a1[i] = ldg_tab(12 + i, t);
    const uint64_t d3 = mkdesc(s23 + 4096, 16, 1024, 1);
#pragma unroll
    for (int c = 0; c < 2; c++) {
        wg_wait<1>();
        TS(11 + c);
        uint32_t pr[2][4], pi[2][4];
#pragma unroll
        for (int i = 0; i < 4; i++) {
            const uint32_t er = X[c][0][i], ei = X[c][0][4 + i], orr = X[c][1][i], oi = X[c][1][4 + i];
            const uint32_t ar = KH[c][0][i], ai = KH[c][0][4 + i], br = KH[c][1][i], bi = KH[c][1][4 + i];
            pr[0][i] = hfms(bi, oi, hfma(br, orr, hfms(ai, ei, hmul(ar, er))));
            pi[0][i] = hfma(bi, orr, hfma(br, oi, hfma(ai, er, hmul(ar, ei))));
            pr[1][i] = hfms(ai, oi, hfma(ar, orr, hfms(bi, ei, hmul(br, er))));
            pi[1][i] = hfma(ai, orr, hfma(ar, oi, hfma(bi, er, hmul(br, ei))));
        }
        wg_fence();
        wgmma_h32_rs(Y[c][0], pr[0], d3, 0);
        wgmma_h32_rs(Y[c][1], pr[1], d3 + 4, 0);
        wgmma_h32_rs(Y[c][0], pi[0], d3 + 2, 1);
        wgmma_h32_rs(Y[c][1], pi[1], d3 + 6, 1);
        wg_commit();
    }
#pragma unroll
    for (int c = 0; c < 2; c++) {
        if (c == 0) wg_wait<1>(); else wg_wait<0>();
        TS(13 + c);
        uint32_t zr[2][4], zi[2][4];
#pragma unroll
        for (int p = 0; p < 2; p++)
#pragma unroll
            for (int i = 0; i < 4; i++) {
                const uint32_t r = Y[c][p][i], m = Y[c][p][4 + i], tr = u4(tw[p], i), ti = u4(tw[2 + p], i);
                zr[i & 1][2 * p + (i >> 1)] = hfma(m, ti, hmul(r, tr));
                zi[i & 1][2 * p + (i >> 1)] = hfms(r, ti, hmul(m, tr));
            }
        const int kr = 4 * (mj >> 1) + (mj & 1) + 2 * (mj >> 2), ki = kr ^ 2;
#pragma unroll
        for (int h = 0; h < 2; h++) {
            const uint32_t a = zb + (2 * w + h) * 2048;
            stsm_x4(a + kr * 128 + (((4 * c + mi) ^ (kr & 7)) << 4), zr[h][0], zr[h][1], zr[h][2], zr[h][3]);
            stsm_x4(a + ki * 128 + (((4 * c + mi) ^ (ki & 7)) << 4), zi[h][0], zi[h][1], zi[h][2], zi[h][3]);
        }
    }
    TS(15);
    fence_async_smem();
    TS(16);
    named_bar(1 + wg, 128);
    TS(17);
    float acc[32];
    const uint64_t dz = mkdesc(zb, 4096, 1024, 1);
    wg_fence();
#pragma unroll
    for (int ks = 0; ks < 4; ks++) wgmma_sp64_rs(acc, a1[ks], dz + ks * 256, 0x44EEEE44u, ks > 0);
    wg_commit();
    wg_wait<0>();
    TS(18);
#pragma unroll
    for (int p = 0; p < 2; p++) {
        uint32_t r[2][2][2];
#pragma unroll
        for (int c = 0; c < 2; c++)
#pragma unroll
            for (int j = 0; j < 2; j++) {
                const float* d = acc + 4 * (4 * c + 2 * p + j);
                const uint32_t y0 = pack2(d[0] + d[2], d[1] + d[3]), y1 = pack2(d[0] - d[2], d[1] - d[3]);
                asm("fma.rn.bf16x2 %0, %1, %2, %3;" : "=r"(r[c][0][j]) : "r"(y0), "r"(oscale[c]), "r"(j ? x[c][0][p].y : x[c][0][p].x));
                asm("fma.rn.bf16x2 %0, %1, %2, %3;" : "=r"(r[c][1][j]) : "r"(y1), "r"(oscale[c]), "r"(j ? x[c][1][p].y : x[c][1][p].x));
            }
#pragma unroll
        for (int h = 0; h < 2; h++) {
            if (layer == 0) {
#pragma unroll
                for (int c = 0; c < 2; c++) *(uint2*)(g_x2T + (size_t)(ch0 + c) * XP + 1024 * p + ra[h]) = make_uint2(r[c][h][0], r[c][h][1]);
            } else {
                const uint32_t v0 = __byte_perm(r[0][h][0], r[1][h][0], 0x5410);
                st_ll4((uint4*)&g_fin[ch0 >> 1][1024 * p + ra[h]], v0 ? v0 : 0x80000000u, __byte_perm(r[0][h][0], r[1][h][0], 0x7632),
                       __byte_perm(r[0][h][1], r[1][h][1], 0x5410), __byte_perm(r[0][h][1], r[1][h][1], 0x7632));
            }
        }
    }
    TS(19);
}

#define Q_SCHED 0
#define Q_WAITFOR(it) (Q_SCHED == 0 ? (it) - 2 : Q_SCHED == 1 ? ((it) == 3 ? 1 : 0) : Q_SCHED == 2 ? -1 : (it) - 1)
#define Q_S0 6
#define Q_WGATE 0
#define CLR_POS 2
#define F_WDELAY 1200
constexpr int Q_ST = 4;
constexpr int Q_AB = 16384, Q_BB = 30720, Q_SB = Q_AB + Q_BB;
constexpr int Q_EROW = 336;
constexpr int Q_ESLOT = 8 * Q_EROW;
constexpr int Q_EOFF = Q_ST * Q_SB;
constexpr int Q_KG = 2 * Q_SB;
constexpr int Q_KDUMP = Q_EOFF + 16384;
static_assert(6 * Q_ESLOT <= 16384, "exchange slots");
static_assert(Q_KG + KG_TABLES <= Q_KDUMP, "kernel generation layout");
constexpr int Q_SMEM = Q_KDUMP + KG_DUMP;
constexpr int F_EO = Q_EOFF, F_S23 = F_EO + 3 * 8192;
static_assert(F_S23 + 8192 <= Q_SMEM, "convolution layout");
__host__ __device__ constexpr int w_main(int j) { return (2 + (j >> 2)) * Q_SB + (j & 3) * 10240; }
__host__ __device__ constexpr int w_rem(int j) { return j < 4 ? (2 + (j >> 1)) * Q_SB + 40960 + (j & 1) * 2560 : 20480 + (j - 4) * 2560; }
constexpr int W_RES = 0, W_OUT = Q_SB;

__device__ unsigned g_epoch;
__device__ __align__(1024) unsigned long long g_stats[SEQ];
__device__ __align__(1024) uint4 g_csp[8][16][80];
__device__ __align__(1024) unsigned g_bar[3][16][32];
__device__ __align__(1024) uint4 g_halo[128][2][7][32];
__device__ __align__(1024) uint4 g_of[8][16][8][5][32];

struct Bars { uint64_t full[Q_ST], empty[Q_ST], wfull[3], ex[8], res, go, qdone, att, prep, kf, ardy, xrdy, fdone, idx, kdone, att1; };
constexpr int NBAR = sizeof(Bars) / 8;
__device__ __forceinline__ void grid_wait(const unsigned* c, int n, unsigned target, int lane) {
    const unsigned* p = c + 32 * min(lane, n - 1);
    unsigned v;
    int spin = 0;
    do { asm volatile("ld.relaxed.gpu.global.u32 %0, [%1];" : "=r"(v) : "l"(p) : "memory"); } while (!__all_sync(~0u, (int)(v - target) >= 0) && ++spin < (1 << 18));
    fence_acquire();
}
__device__ __forceinline__ void grid_arrive(unsigned* c) {
    fence_release();
    asm volatile("red.relaxed.gpu.global.add.u32 [%0], 1;" ::"l"(c) : "memory");
}

__global__ void __launch_bounds__(384, 1)
fused_kernel(const __grid_constant__ CUtensorMap mX0, const __grid_constant__ CUtensorMap mX1, const __grid_constant__ CUtensorMap mW,
             const __grid_constant__ CUtensorMap mWr, const __grid_constant__ CUtensorMap mWo, const __grid_constant__ CUtensorMap mWor,
             const __grid_constant__ CUtensorMap mRes0, const __grid_constant__ CUtensorMap mRes1, const __grid_constant__ CUtensorMap mOut,
             const bf16* __restrict__ xin, const bf16* __restrict__ wqkv, const bf16* __restrict__ wo, bf16* __restrict__ out, const SsmParams sp) {
    extern __shared__ __align__(1024) char smraw[];
    __shared__ __align__(8) Bars s_bar[2];
    __shared__ __align__(16) float s_cs[240], s_mean[2][72], s_rstd[2][72], s_red[3][32];
    __shared__ KgShared s_kg;
    __shared__ uint32_t s_epoch;
    const uint32_t sb = s2u(smraw);
    int tid, warp, lane, bx, rank, blk, hg, npair, pair0, srow;
    auto indices = [&] {
        asm volatile("mov.u32 %0, %%tid.x;" : "=r"(tid));
        asm volatile("mov.u32 %0, %%ctaid.x;" : "=r"(bx));
        warp = __shfl_sync(~0u, tid >> 5, 0); lane = tid & 31;
        rank = bx & 1; blk = bx & 15; hg = bx >> 4;
        npair = 3 - rank; pair0 = 5 * (bx >> 1) + 3 * rank;
        srow = 1024 * (hg >> 2) + 64 * blk + 16 * (hg & 3);
    };
    indices();
    TS_DECL;
    TS_BEGIN;
    KgParams kp;
    kgen_load(kp, bx * 5, warp, lane, sp);
    const uint32_t epoch0 = ldg32(&g_epoch);
#define EPOCH lds32(s2u(&s_epoch))
#define TAG (2u * EPOCH + layer + 1u)
    if (tid < 64) g_sums[0][0][(tid >> 4) * SEQ + srow + (tid & 15)] = 0.f;
    if (tid < 5) s_kg.kmax[tid] = 0u;
    if (tid == 256) { prefetch_tmap(&mW); prefetch_tmap(&mWr); prefetch_tmap(&mX0); }
    if (tid == 320) { prefetch_tmap(&mWo); prefetch_tmap(&mWor); prefetch_tmap(&mRes0); prefetch_tmap(&mOut); prefetch_tmap(&mX1); prefetch_tmap(&mRes1); }
    if (tid >= 128) sts128(sb + Q_EOFF + 4096 + (tid - 128) * 16, make_uint4(0, 0, 0, 0));
    if (elect_one()) {
#define BAR_IS(f) (i == offsetof(Bars, f) / 8)
#pragma unroll 1
        for (int i = warp; i < NBAR; i += 12) {
            const int cnt = (i >= 4 && i < 8) ? 16 : (BAR_IS(go) || BAR_IS(att1)) ? 4 : (BAR_IS(qdone) || BAR_IS(att)) ? 8 : BAR_IS(prep) ? 96 : BAR_IS(fdone) ? npair : BAR_IS(kdone) ? 2 : 1;
            mbar_init(s2u(s_bar) + i * 8, cnt);
            mbar_init(s2u(s_bar) + (NBAR + i) * 8, cnt);
        }
        fence_mbar_init();
    }
    __syncwarp();
    TS(29);
    fence_async_smem();
    TS(30);
    __syncthreads();
    TS(31);
    cluster_arrive_relaxed();
    auto clear = [&] {
#pragma unroll 1
        for (int i = 0; i < 5; i++) {
            bulk_s2g((char*)&g_of[hg][blk] + i * 4096, sb + Q_EOFF + 4096, 4096);
            bulk_s2g((char*)g_fin + (bx * 5 + i) * 4096, sb + Q_EOFF + 4096, 4096);
        }
        bulk_commit();
    };
    cluster_wait();
    TS(27);

    int layer = 0;
    uint32_t bars = s2u(s_bar);
#define BAR(f) (bars + (uint32_t)offsetof(Bars, f))
    auto issue_w = [&](uint32_t bb, int it, int half) {
        const int s = it & (Q_ST - 1);
        const uint32_t fb = bb + 8 * s, db = sb + s * Q_SB + Q_AB + half * 15360;
        const int k0 = it * 64 + half * 32;
#pragma unroll
        for (int p = 0; p < 3; p++) tma2d_mc(db + p * 4096, &mW, p * DM + hg * 80, k0, fb, 3);
        tma3d_mc(db + 12288, &mWr, hg * 80 + 64, k0, 0, fb, 3);
    };
    auto issue_x = [&](int it) {
        const int s = it & (Q_ST - 1);
        mbar_expect(BAR(full) + 8 * s, Q_SB);
        tma3d(sb + s * Q_SB, layer ? &mX1 : &mX0, (layer ? blk : it) * 64, (layer ? it : blk) * 64, 0, BAR(full) + 8 * s);
    };
    {
        auto F = [](uint32_t x) { return __uint_as_float(x); };
        const int t2 = tid & 127, cl = min(lane, 29);
        const bf16* wsrc = wqkv + (size_t)(40 * blk + 10 * (warp & 3)) * (3 * DM) + (cl / 10) * DM + hg * 80 + 8 * (cl % 10);
        const bf16* xsrc = xin + (size_t)(2 * ((srow & 1023) + (t2 >> 3)) + (hg >> 2)) * DM + 8 * (t2 & 7);
        if (warp == 8) {
            if (elect_one()) {
#pragma unroll 1
                for (int it = 0; it < 2; it++) { issue_w(BAR(full), it, rank); issue_x(it); }
                mbar_expect(BAR(idx), 4096);
                bulk_g2s(sb + Q_KDUMP + KG_IDX, c_fft + 16 * 512, 4096, BAR(idx));
            }
            __syncwarp();
        }
        kgen_tables(kp, sb + Q_KG, sb + Q_KDUMP, warp, lane, [&] {
            if (tid == 256) s_epoch = epoch0;
            if (warp >= 8) {
                const char* wp = (const char*)(wqkv + (size_t)(40 * blk + min(t2, 119) / 3) * (3 * DM) + (t2 % 3) * DM + hg * 80);
                prefetch_l2(wp); prefetch_l2(wp + 128); prefetch_l2(wp + 159);
                prefetch_l2(xsrc + 56 * (t2 & 7));
                if ((t2 & 7) < 2) prefetch_l2(xsrc + 56 * (t2 & 7) + 512);
            } else {
                if (tid < 50) prefetch_l2((const char*)wo + (size_t)(bx * 50 + tid) * 128);
                if (tid >= 64 && tid < 67 && bx * 3 + tid - 64 < sizeof(c_fft) / 128) prefetch_l2((const char*)c_fft + (size_t)(bx * 3 + tid - 64) * 128);
            }
        } TS_PASS);
        if (warp <= 8) asm volatile("bar.arrive 8, 384;" ::: "memory");
        fence_async_smem();
        cluster_arrive_relaxed();
        TS(1);
        if (warp >= 8) {
            if (tid == 288) clear();
            __syncwarp();
            uint4 v[10], u[10];
#pragma unroll
            for (int i = 0; i < 10; i++) v[i] = __ldg((const uint4*)(wsrc + (size_t)i * (3 * DM)));
#pragma unroll
            for (int i = 0; i < 10; i++) u[i] = __ldg((const uint4*)(xsrc + 64 * i));
            const uint32_t tag = TAG;
            float cs[8] = {0.f, 0.f, 0.f, 0.f, 0.f, 0.f, 0.f, 0.f}, a = 0.f, b = 0.f;
#pragma unroll
            for (int i = 0; i < 10; i++)
#pragma unroll
                for (int j = 0; j < 4; j++) { cs[2 * j] += bf_lo(u4(v[i], j)); cs[2 * j + 1] += bf_hi(u4(v[i], j)); }
            const uint32_t pa = sb + Q_EOFF + 8192;
            if (lane < 30) {
                sts128(pa + ((warp & 3) * 240 + 8 * lane) * 4, make_uint4(__float_as_uint(cs[0]), __float_as_uint(cs[1]), __float_as_uint(cs[2]), __float_as_uint(cs[3])));
                sts128(pa + ((warp & 3) * 240 + 8 * lane + 4) * 4, make_uint4(__float_as_uint(cs[4]), __float_as_uint(cs[5]), __float_as_uint(cs[6]), __float_as_uint(cs[7])));
            }
#pragma unroll
            for (int i = 0; i < 10; i++)
#pragma unroll
                for (int j = 0; j < 4; j++) {
                    const float lo = bf_lo(u4(u[i], j)), hi = bf_hi(u4(u[i], j));
                    a += lo + hi; b = fmaf(lo, lo, fmaf(hi, hi, b));
                }
#pragma unroll
            for (int o = 1; o <= 4; o <<= 1) { a += __shfl_xor_sync(~0u, a, o); b += __shfl_xor_sync(~0u, b, o); }
            if ((t2 & 7) == 0) { s_red[0][t2 >> 3] = a; s_red[0][16 + (t2 >> 3)] = b; }
            named_bar(7, 128);
            if (t2 >= 48) {
                const int i = t2 - 48;
                float t[3];
#pragma unroll
                for (int j = 0; j < 3; j++)
                    t[j] = (F(lds32(pa + (3 * i + j) * 4)) + F(lds32(pa + (240 + 3 * i + j) * 4))) + (F(lds32(pa + (480 + 3 * i + j) * 4)) + F(lds32(pa + (720 + 3 * i + j) * 4)));
                st_ll4(&g_csp[hg][blk][i], __float_as_uint(t[0]), __float_as_uint(t[1]), __float_as_uint(t[2]), tag);
            }
            __syncwarp();
            TS(3);
        }
    }

#pragma unroll 1
    for (; layer < 2; layer++, bars += sizeof(Bars)) {
    indices();
    TS_PHASE(2 * layer);
    if (warp >= 8) {
        asm volatile("setmaxnreg.dec.sync.aligned.u32 88;");
        if (warp == 8) {
            if (layer == 0) {
                cluster_wait();
            } else {
                grid_wait(g_bar[2][0], 12, 32 * (EPOCH + 1), lane);
                if (lane == 0) mbar_arrive(BAR(xrdy));
                mbar_wait(BAR(fdone) - sizeof(Bars), 0);
                fence_async_global();
                TS(1);
            }
            if (elect_one()) {
#pragma unroll 1
                for (int it = layer ? 0 : 2; it < 10; it++) {
                    if (it >= Q_ST) mbar_wait(BAR(empty) + 8 * (it & (Q_ST - 1)), ((it >> 2) - 1) & 1);
                    else if (it > 0 && Q_WAITFOR(it) >= 0) mbar_wait(BAR(full) + 8 * Q_WAITFOR(it), 0);
                    issue_x(it);
                    if (it >= Q_ST || layer == 0) issue_w(BAR(full), it, rank);
                }
#pragma unroll 1
                for (int b = 0; b < 3; b++) {
                    const uint32_t fb = BAR(wfull) + 8 * (b);
                    mbar_wait(BAR(empty) + 8 * ((2 + b) & 3), b < 2);
                    TS(11 + b);
                    if (b == 2) {
                        mbar_expect(BAR(res), 20480);
                        if (layer == 0) tma3d(sb + W_RES, &mX0, hg * 80, blk * 64, 0, BAR(res));
                        tma3d(sb + W_RES + (layer ? 0 : 16384), layer ? &mRes1 : &mRes0, layer ? blk * 64 : hg * 80 + 64, layer ? hg * 80 : blk * 64, 0, BAR(res));
                    }
                    mbar_expect(fb, b < 2 ? 46080 : 10240);
#pragma unroll 1
                    for (int i = 0; i < 4; i++) {
                        if (b < 2) tma2d_mc(sb + w_main(4 * b) + i * 10240 + rank * 5120, &mWo, hg * 80, ((hg + 4 * b + i) & 7) * 80 + rank * 40, fb, 3);
                        if (b == 2 || i < 2) tma2d_mc(sb + w_rem(2 * b) + i * 2560 + rank * 1280, &mWor, hg * 80 + 64, ((hg + 2 * b + i) & 7) * 80 + rank * 40, fb, 3);
                    }
                }
                if (layer == 0) { mbar_wait(BAR(kdone), 0); fence_async_global(); }
                mbar_wait(BAR(att), 0);
                mbar_expect(BAR(kf), (npair + 1 - layer) * 8192);
                bulk_g2s(sb + F_EO, g_keo[pair0], npair * 8192, BAR(kf));
                if (layer == 0) bulk_g2s(sb + F_S23, c_fft + 18 * 512, 8192, BAR(kf));
            }
            __syncwarp();
        } else {
            const int ht = tid - 288, hw = warp - 9;
            auto F = [](uint32_t x) { return __uint_as_float(x); };
            const uint32_t tag = TAG;
            if (layer == 0) {
                if (ht == 0) { bulk_wait(); fence_async_global(); }
                __syncwarp();
                if (ht < 16) {
                    fence_release();
                    st_ll(g_stats + srow + ht, ln_finish_packed(s_red[0][ht], s_red[0][16 + ht]), tag);
                }
            } else {
                mbar_wait(BAR(xrdy), 0);
                if (ht == 0) TSX(2, 2);
                const bf16* src = g_x2T + (size_t)(ht >> 1) * XP + srow + 8 * (lane & 1);
                uint4 v[14];
#pragma unroll
                for (int i = 0; i < 14; i++) {
                    v[i] = make_uint4(0, 0, 0, 0);
                    if (i < 13 || hw == 0) v[i] = ldg128(src + (size_t)48 * i * XP);
                }
                float a[16];
#pragma unroll
                for (int j = 0; j < 16; j++) a[j] = 0.f;
#pragma unroll
                for (int i = 0; i < 14; i++)
#pragma unroll
                    for (int j = 0; j < 4; j++) {
                        const float lo = bf_lo(u4(v[i], j)), hi = bf_hi(u4(v[i], j));
                        a[2 * j] += lo; a[8 + 2 * j] = fmaf(lo, lo, a[8 + 2 * j]); a[2 * j + 1] += hi; a[9 + 2 * j] = fmaf(hi, hi, a[9 + 2 * j]);
                    }
                if (ht == 0) TSX(2, 8);
#pragma unroll
                for (int l = 0; l < 4; l++) {
                    const int n = 8 >> l;
                    const bool up = lane & (2 * n);
#pragma unroll
                    for (int j = 0; j < 8; j++)
                        if (j < n) { const float lo = a[j], hi = a[j + n]; a[j] = (up ? hi : lo) + __shfl_xor_sync(~0u, up ? lo : hi, 2 * n); }
                }
                s_red[hw][(lane & 16) + 8 * (lane & 1) + ((lane >> 1) & 7)] = a[0];
                named_bar(4, 96);
                if (ht < 16) st_ll(g_stats + srow + ht, ln_finish_packed(s_red[0][ht] + s_red[1][ht] + s_red[2][ht], s_red[0][16 + ht] + s_red[1][16 + ht] + s_red[2][16 + ht]), tag);
            }
            if (ht == 0) TSX(2, 4);
            if (layer == 0 && ht < 80) {
                float t[3] = {0.f, 0.f, 0.f};
                uint4 v[16];
                int spin = 0;
                bool ok;
                do {
                    ok = true;
#pragma unroll
                    for (int j = 0; j < 16; j++) v[j] = ld_ll4(&g_csp[hg][j][ht]);
#pragma unroll
                    for (int j = 0; j < 16; j++) ok = ok && v[j].w == tag;
                } while (!ok && ++spin < (1 << 18));
#pragma unroll
                for (int j = 0; j < 16; j++) { t[0] += F(v[j].x); t[1] += F(v[j].y); t[2] += F(v[j].z); }
#pragma unroll
                for (int j = 0; j < 3; j++) s_cs[3 * ht + j] = t[j];
            }
            if (ht == 0) TSX(2, 15);
            if (ht < 72) {
                const unsigned long long* sp0 = g_stats + 64 * blk + ((blk || ht >= 8) ? ht - 8 : 0);
                unsigned long long v0, v1;
                int spin = 0;
                do { v0 = ld_ll(sp0); v1 = ld_ll(sp0 + 1024); } while (((uint32_t)(v0 >> 32) != tag || (uint32_t)(v1 >> 32) != tag) && ++spin < (1 << 18));
                s_mean[0][ht] = bf_hi((uint32_t)v0); s_rstd[0][ht] = frcp(bf_lo((uint32_t)v0));
                s_mean[1][ht] = bf_hi((uint32_t)v1); s_rstd[1][ht] = frcp(bf_lo((uint32_t)v1));
            }
            fence_acquire();
            mbar_arrive(BAR(prep));
            if (ht == 0) TSX(2, 5);
            if (layer == 0) {
                __syncwarp();
                cluster_wait();
                named_bar(8, 384);
                mbar_wait(BAR(idx), 0);
                kgen_expand(bx * 5, sb + Q_KDUMP, &s_kg, ht TS_PASS);
                fence_async_smem();
                named_bar(4, 96);
                if (ht == 0) { fence_release(); mbar_arrive_cta(BAR(kdone), 0); mbar_arrive_cta(BAR(kdone), 1); }
                if (ht == 0) TSX(2, 7);
            }
        }
        __syncwarp();
        named_bar(3, 128);
        asm volatile("setmaxnreg.inc.sync.aligned.u32 168;");
    } else {
    asm volatile("setmaxnreg.inc.sync.aligned.u32 208;");
    const int wg = warp >> 2, w = warp & 3;
    const int mi = lane >> 3, mj = lane & 7, g = lane >> 2, q = lane & 3;
    TS(2);
    float acc[120];
#pragma unroll
    for (int i = 0; i < 120; i++) acc[i] = 0.f;
    auto release = [&](int it) {
        if (lane == 0) { mbar_arrive_cta(BAR(empty) + 8 * (it & (Q_ST - 1)), 0); mbar_arrive_cta(BAR(empty) + 8 * (it & (Q_ST - 1)), 1); }
    };
#pragma unroll 1
    for (int it = 0; it < 10; it++) {
        const int s = it & (Q_ST - 1);
        const uint32_t st = sb + s * Q_SB;
        const bool hold = wg == 1 && it == Q_S0;
        if (hold) {
            wg_wait<0>();
            release(it - 1);
            mbar_wait(BAR(go), 0);
        }
        mbar_wait(BAR(full) + 8 * (s), (it >> 2) & 1);
        if (it < 2) TS(3 + it);
        if (it == 6) TS(5);
        if (it == 9) TS(6);
        const uint64_t da = mkdesc(st + wg * 8192, 16, 1024, 1);
        const uint64_t db = mkdesc(st + Q_AB, 4096, 1024, 1);
        const uint64_t dr = mkdesc(st + Q_AB + 12288, 1024, 256, 3);
        if (layer == 0) {
            wg_fence();
#pragma unroll
            for (int ks = 0; ks < 4; ks++) {
                const int sc = 1;
                wgmma_n192<0, 1>(*(float(*)[96]) & acc[0], da + ks * 2, db + (ks >> 1) * 960 + (ks & 1) * 128, sc);
                wgmma_n48<0, 1>(*(float(*)[24]) & acc[96], da + ks * 2, dr + (ks >> 1) * 960 + (ks & 1) * 32, sc);
            }
            wg_commit();
        } else {
            wg_fence();
#pragma unroll
            for (int ks = 0; ks < 4; ks++) {
                const int sc = 1;
                wgmma_n192<1, 1>(*(float(*)[96]) & acc[0], da + ks * 128, db + (ks >> 1) * 960 + (ks & 1) * 128, sc);
                wgmma_n48<1, 1>(*(float(*)[24]) & acc[96], da + ks * 128, dr + (ks >> 1) * 960 + (ks & 1) * 32, sc);
            }
            wg_commit();
        }
        wg_wait<1>();
        if (it > 0 && !hold) release(it - 1);
    }
    if (wg == 0 && lane == 0) mbar_arrive(BAR(go));
    if (layer == 0) cluster_wait();
    mbar_wait(BAR(prep), 0);
    const uint32_t tag = TAG;
    const bool first = (blk == 0 && w == 0);
    const bool sel0 = (2 * q > g), sel1 = (2 * q + 1 > g);
    constexpr float SC = 0.22360679774997896f * 1.4426950408889634f;
    const float m0 = s_mean[wg][8 + 16 * w + g], m1 = s_mean[wg][16 + 16 * w + g];
    const float* rs = &s_rstd[wg][16 * w];
    const float kx0 = rs[2 * q + (sel0 ? 0 : 8)], kx1 = rs[2 * q + (sel1 ? 1 : 9)], ky0 = rs[2 * q + (sel0 ? 8 : 16)], ky1 = rs[2 * q + (sel1 ? 9 : 17)];
    const float cx0 = SC * rs[8 + g] * kx0, cx1 = SC * rs[8 + g] * kx1, cy0 = SC * rs[16 + g] * ky0, cy1 = SC * rs[16 + g] * ky1;
    wg_wait<0>();
    TS(7);
    if (lane == 0) mbar_arrive(BAR(qdone));
    uint32_t ql[10], qh[10], kl[10], kh[10], vl[10], vh[10];
    auto fold = [&](int p, int f, uint32_t& lo, uint32_t& hi) {
        const int j = (f < 8) ? 8 * p + f : 24 + 2 * p + (f - 8);
        const float2 c = *(const float2*)&s_cs[p * 80 + 8 * f + 2 * q];
        lo = pack2(fmaf(-m0, c.x, acc[4 * j]), fmaf(-m0, c.y, acc[4 * j + 1]));
        hi = pack2(fmaf(-m1, c.x, acc[4 * j + 2]), fmaf(-m1, c.y, acc[4 * j + 3]));
    };
#pragma unroll
    for (int f = 0; f < 10; f++) { fold(1, f, kl[f], kh[f]); fold(2, f, vl[f], vh[f]); }
    if (w == 3) {
        uint4* hp = &g_halo[bx][wg][0][lane];
        st_ll4(hp, kh[0], kh[1], kh[2], tag); st_ll4(hp + 32, kh[3], kh[4], kh[5], tag); st_ll4(hp + 64, kh[6], kh[7], kh[8], tag);
        st_ll4(hp + 96, kh[9], vh[0], vh[1], tag); st_ll4(hp + 128, vh[2], vh[3], vh[4], tag); st_ll4(hp + 160, vh[5], vh[6], vh[7], tag);
        st_ll4(hp + 192, vh[8], vh[9], 0u, tag);
    } else {
        const uint32_t a = sb + Q_EOFF + (warp - wg) * Q_ESLOT + mj * Q_EROW + mi * 16;
        stsm_x4(a, kh[0], kh[1], kh[2], kh[3]);
        stsm_x4(a + 64, kh[4], kh[5], kh[6], kh[7]);
        stsm_x4(a + 128, kh[8], kh[9], vh[0], vh[1]);
        stsm_x4(a + 192, vh[2], vh[3], vh[4], vh[5]);
        stsm_x4(a + 256, vh[6], vh[7], vh[8], vh[9]);
        __syncwarp();
        if (lane == 0) mbar_arrive(BAR(ex) + 8 * (warp));
    }
    TS(9);
#pragma unroll
    for (int f = 0; f < 10; f++) fold(0, f, ql[f], qh[f]);
    uint32_t vt1[10], vt2[10];
#pragma unroll
    for (int f = 0; f < 10; f++) { vt1[f] = movm_t(vl[f]); vt2[f] = movm_t(vh[f]); }
    TS(10);
    uint32_t kp[10], vp[10];
    if (w > 0) {
        const uint32_t a = sb + Q_EOFF + (warp - wg - 1) * Q_ESLOT + mj * Q_EROW + mi * 16;
        mbar_wait(BAR(ex) + 8 * (warp - 1), 0);
        ldsm_x4(kp[0], kp[1], kp[2], kp[3], a);
        ldsm_x4(kp[4], kp[5], kp[6], kp[7], a + 64);
        ldsm_x2(kp[8], kp[9], a + 128);
        ldsm_x4_t(vp[0], vp[1], vp[2], vp[3], a + 160);
        ldsm_x4_t(vp[4], vp[5], vp[6], vp[7], a + 224);
        ldsm_x2_t(vp[8], vp[9], a + 288 - (lane >> 4) * 32);
    } else if (blk > 0) {
        const uint4* hp = &g_halo[bx - 1][wg][0][lane];
        uint4 hv[7];
        int spin = 0;
        bool ok;
        do {
            ok = true;
#pragma unroll
            for (int f = 0; f < 7; f++) hv[f] = ld_ll4(hp + 32 * f);
#pragma unroll
            for (int f = 0; f < 7; f++) ok = ok && hv[f].w == tag;
        } while (!__all_sync(~0u, ok) && ++spin < (1 << 18));
#pragma unroll
        for (int f = 0; f < 10; f++) { kp[f] = u4(hv[f / 3], f % 3); vp[f] = movm_t(u4(hv[(10 + f) / 3], (10 + f) % 3)); }
    } else {
#pragma unroll
        for (int f = 0; f < 10; f++) { kp[f] = 0u; vp[f] = 0u; }
    }
    fence_async_smem();
    __syncwarp();
    if (lane == 0) mbar_arrive(BAR(att));
    TS(12);
    float oacc[10][4];
#pragma unroll
    for (int h = 0; h < 4; h++) {
        const int fa = (h == 0) ? 0 : (h == 1) ? 3 : (h == 2) ? 5 : 8, fb = fa + 1, fh = (h < 2) ? 2 : 7;
        const bool mine = (h & 1) ? (q >= 2) : (q < 2);
        const uint32_t qml = mine ? ql[fh] : 0u, qmh = mine ? qh[fh] : 0u;
        float S0[4] = {0.f, 0.f, 0.f, 0.f}, S1[4] = {0.f, 0.f, 0.f, 0.f}, S2[4] = {0.f, 0.f, 0.f, 0.f};
        mma16816(S0, ql[fa], qh[fa], ql[fb], qh[fb], kp[fa], kp[fb]); mma1688(S0, qml, qmh, kp[fh]);
        mma16816(S1, ql[fa], qh[fa], ql[fb], qh[fb], kl[fa], kl[fb]); mma1688(S1, qml, qmh, kl[fh]);
        mma16816(S2, ql[fa], qh[fa], ql[fb], qh[fb], kh[fa], kh[fb]); mma1688(S2, qml, qmh, kh[fh]);
        float x0 = (sel0 ? S0[0] : S1[0]) * cx0, x1 = (sel1 ? S0[1] : S1[1]) * cx1;
        float y0 = (sel0 ? S1[2] : S2[2]) * cy0, y1 = (sel1 ? S1[3] : S2[3]) * cy1;
        if (first) { if (sel0) x0 = -INFINITY; if (sel1) x1 = -INFINITY; }
        float mx = fmaxf(x0, x1), my = fmaxf(y0, y1);
        mx = fmaxf(mx, __shfl_xor_sync(~0u, mx, 1)); my = fmaxf(my, __shfl_xor_sync(~0u, my, 1));
        mx = fmaxf(mx, __shfl_xor_sync(~0u, mx, 2)); my = fmaxf(my, __shfl_xor_sync(~0u, my, 2));
        x0 = ex2(x0 - mx); x1 = ex2(x1 - mx); y0 = ex2(y0 - my); y1 = ex2(y1 - my);
        float sx = x0 + x1, sy = y0 + y1;
        sx += __shfl_xor_sync(~0u, sx, 1); sy += __shfl_xor_sync(~0u, sy, 1);
        sx += __shfl_xor_sync(~0u, sx, 2); sy += __shfl_xor_sync(~0u, sy, 2);
        const float ix = frcp(sx), iy = frcp(sy);
        x0 *= ix * kx0; x1 *= ix * kx1; y0 *= iy * ky0; y1 *= iy * ky1;
        const uint32_t pa0 = pack2(sel0 ? x0 : 0.f, sel1 ? x1 : 0.f);
        const uint32_t pa2 = pack2(sel0 ? 0.f : x0, sel1 ? 0.f : x1);
        const uint32_t pa3 = pack2(sel0 ? y0 : 0.f, sel1 ? y1 : 0.f);
        const uint32_t pb1 = pack2(sel0 ? 0.f : y0, sel1 ? 0.f : y1);
#pragma unroll
        for (int i = 0; i < 3; i++) {
            const int f = (i == 0) ? fa : (i == 1) ? fb : fh;
            float O[4] = {0.f, 0.f, 0.f, 0.f};
            mma16816(O, pa0, 0u, pa2, pa3, vp[f], vt1[f]);
            mma1688(O, 0u, pb1, vt2[f]);
            if (i < 2 || !(h & 1) || mine) { oacc[f][0] = O[0]; oacc[f][1] = O[1]; oacc[f][2] = O[2]; oacc[f][3] = O[3]; }
        }
    }
    TS(13);
    uint4 of[5][5];
    {
        uint4* dst = &g_of[hg][blk][warp][0][lane];
#pragma unroll
        for (int k = 0; k < 5; k++) {
            of[0][k] = make_uint4(pack2(oacc[2 * k][0], oacc[2 * k][1]), pack2(oacc[2 * k][2], oacc[2 * k][3]),
                                  pack2(oacc[2 * k + 1][0], oacc[2 * k + 1][1]), pack2(oacc[2 * k + 1][2], oacc[2 * k + 1][3]));
            st_ll4(dst + 32 * k, of[0][k].x ? of[0][k].x : 0x80000000u, of[0][k].y, of[0][k].z, of[0][k].w);
        }
    }
    if (Q_WGATE && wg == 1 && lane == 0) mbar_arrive(BAR(att1));
    TS(14);
    const uint4* osrc = &g_of[0][blk][warp][0][lane];
    auto oload = [&](int j) {
        const uint4* p = osrc + ((hg + j) & 7) * 20480;
#pragma unroll
        for (int k = 0; k < 5; k++) of[j % 5][k] = ld_ll4(p + 32 * k);
    };
    {
        const uint32_t* pp = &g_of[(hg + 1 + (lane & 3)) & 7][blk][warp][4][31].x;
        uint32_t v;
        int spin = 0;
        do { asm volatile("ld.relaxed.gpu.global.u32 %0, [%1];" : "=r"(v) : "l"(pp) : "memory"); } while (!__all_sync(~0u, v != 0u) && ++spin < (1 << 18));
    }
    TS(15);
#pragma unroll
    for (int j = 1; j < 5; j++) oload(j);
    float a64[32], a16[8];
    if (Q_WGATE && wg == 0) mbar_wait(BAR(att1), 0);
#pragma unroll
    for (int j = 0; j < 8; j++) {
        if (j == 0 || j == 2 || j == 4) mbar_wait(BAR(wfull) + 8 * (j >> 1), 0);
        if (j > 0) {
            int spin = 0;
            while (true) {
                bool ok = true;
#pragma unroll
                for (int k = 0; k < 5; k++) ok = ok && of[j % 5][k].x != 0u;
                if (__all_sync(~0u, ok) || ++spin >= (1 << 18)) break;
                oload(j);
            }
        }
        if (j == 0) TS(16);
        if (j == 1) TS(17);
        if (j == 5) TS(18);
        const uint64_t dm = mkdesc(sb + w_main(j), 4096, 1024, 1), dr = mkdesc(sb + w_rem(j), 1024, 256, 3);
        wg_fence();
#pragma unroll
        for (int k = 0; k < 5; k++) {
            wgmma_rs64(a64, of[j % 5][k], dm + k * 128, j + k > 0);
            wgmma_rs16(a16, of[j % 5][k], dr + k * 32, j + k > 0);
        }
        wg_commit();
        if (j >= 1 && j <= 3) { wg_wait<1>(); oload(j + 4); }
    }
    uint32_t res[20];
    mbar_wait(BAR(res), 0);
    const uint32_t ta = (8 * (mi >> 1) + mj) * 128 + (((2 * w + (mi & 1)) ^ mj) << 4);
    if (layer == 0) {
        const int tok = 16 * w + 8 * (mi & 1) + mj;
#pragma unroll
        for (int k = 0; k < 4; k++)
            ldsm_x4(res[4 * k], res[4 * k + 1], res[4 * k + 2], res[4 * k + 3], sb + W_RES + wg * 8192 + tok * 128 + (((2 * k + (mi >> 1)) ^ mj) << 4));
        ldsm_x4(res[16], res[17], res[18], res[19], sb + W_RES + 16384 + wg * 2048 + tok * 32 + (((mi >> 1) ^ (mj >> 2)) << 4));
    } else {
#pragma unroll
        for (int k = 0; k < 5; k++) ldsm_x4_t(res[4 * k], res[4 * k + 1], res[4 * k + 2], res[4 * k + 3], sb + W_RES + wg * 10240 + k * 2048 + ta);
    }
    mbar_wait(BAR(qdone), 0);
    wg_wait<0>();
    TS(19);
#pragma unroll
    for (int i = 0; i < 20; i++) {
        const uint32_t y = i < 16 ? pack2(a64[2 * i], a64[2 * i + 1]) : pack2(a16[2 * i - 32], a16[2 * i - 31]);
        asm("add.rn.bf16x2 %0, %0, %1;" : "+r"(res[i]) : "r"(y));
    }
#pragma unroll
    for (int k = 0; k < 5; k++) stsm_x4_t(sb + W_OUT + wg * 10240 + k * 2048 + ta, res[4 * k], res[4 * k + 1], res[4 * k + 2], res[4 * k + 3]);
    fence_async_smem();
    named_bar(1 + wg, 128);
    if ((tid & 127) == 0) {
        asm volatile("cp.async.bulk.tensor.2d.global.shared::cta.bulk_group [%0, {%2, %3}], [%1];"
                     ::"l"(&mOut), "r"(sb + W_OUT + wg * 10240), "r"(1024 * wg + 64 * blk), "r"(hg * 80) : "memory");
        bulk_commit();
    }
    TS(20);
    {
        float sm[4] = {0.f, 0.f, 0.f, 0.f}, d0[4] = {0.f, 0.f, 0.f, 0.f}, d1[4] = {0.f, 0.f, 0.f, 0.f};
#pragma unroll
        for (int k = 0; k < 5; k++) {
            mma16816(sm, res[4 * k], res[4 * k + 1], res[4 * k + 2], res[4 * k + 3], 0x3F803F80u, 0x3F803F80u);
            mma16816(d0, res[4 * k], res[4 * k + 1], res[4 * k + 2], res[4 * k + 3], res[4 * k], res[4 * k + 2]);
            mma16816(d1, res[4 * k], res[4 * k + 1], res[4 * k + 2], res[4 * k + 3], res[4 * k + 1], res[4 * k + 3]);
        }
        const bool diag = q == (g >> 1);
        if (diag || q == ((g >> 1) ^ 1)) {
            float* dst = g_sums[layer][diag] + 1024 * wg + 64 * blk + 16 * w + g;
            asm volatile("red.global.add.f32 [%0], %1;" ::"l"(dst), "f"(diag ? ((g & 1) ? d0[1] : d0[0]) : sm[0]) : "memory");
            asm volatile("red.global.add.f32 [%0], %1;" ::"l"(dst + 8), "f"(diag ? ((g & 1) ? d1[3] : d1[2]) : sm[2]) : "memory");
        }
    }
    TS(21);
    named_bar(1 + wg, 128);
    if ((tid & 127) == 0) { bulk_wait(); fence_async_global(); grid_arrive(g_bar[layer][hg]); }
    __syncwarp();
    asm volatile("setmaxnreg.dec.sync.aligned.u32 168;");
    TS(22);
    }
    TS_PHASE(2 * layer + 1);
    TS(0);
    indices();
    const int wg = warp >> 2;
    if (wg < npair) {
        conv_pair(2 * (pair0 + wg), layer, sb + F_EO + wg * 8192, sb + wg * Q_SB, sb + F_S23, BAR(kf), warp, lane, [&] {
            if (warp == 0) {
                grid_wait(g_bar[layer][0], 8, 32 * (EPOCH + 1), lane);
                if (lane == 0) mbar_arrive(BAR(ardy));
            } else {
                mbar_wait(BAR(ardy), 0);
            }
        } TS_PASS);
        if (layer == 0) {
            named_bar(1 + wg, 128);
            if ((tid & 127) == 0) { mbar_arrive(BAR(fdone)); grid_arrive(g_bar[2][(pair0 + wg) >> 5]); }
            __syncwarp();
        }
    } else if (layer == 0) {
#pragma unroll
        for (int i = 0; i < 4; i++) sts128(sb + F_EO + 2 * 8192 + (tid - 256 + 128 * i) * 16, make_uint4(0, 0, 0, 0));
        fence_async_smem();
        named_bar(3, 128);
        if (warp == 8 || warp == 9) {
            mbar_wait(BAR(ardy), 0);
            const long long t0 = clock64();
            while (clock64() - t0 < F_WDELAY) {}
            if (elect_one()) {
                if (warp == 8) {
#pragma unroll 1
                    for (int i = 0; i < 2 * Q_ST; i++) issue_w(BAR(full) + sizeof(Bars), i >> 1, i & 1);
                } else {
                    fence_async_global();
#pragma unroll 1
                    for (int i = 0; i < 5; i++) bulk_s2g((char*)&g_of[hg][blk - 1] + i * 8192, sb + F_EO + 2 * 8192, 8192);
                    bulk_commit();
                    bulk_wait();
                    fence_async_global();
                    grid_arrive(g_bar[2][10 + (hg >> 2)]);
                }
            }
            __syncwarp();
        }
        named_bar(3, 128);
    }
    TS(20);
    }
    indices();
    if (tid < 320) {
        const int cq = tid % 10, tg = tid / 10;
        const uint4* src = (const uint4*)&g_fin[40 * hg + 4 * cq][1024 * (tg >> 4) + 64 * blk + 4 * (tg & 15)];
        uint4 v[4];
        int spin = 0;
        bool ok;
        do {
            ok = true;
#pragma unroll
            for (int i = 0; i < 4; i++) v[i] = ld_ll4(src + i * (SEQ / 4));
#pragma unroll
            for (int i = 0; i < 4; i++) ok = ok && v[i].x != 0u;
        } while (!ok && ++spin < (1 << 18));
        TS(21);
        bf16* dst = out + (size_t)(128 * blk + 8 * (tg & 15) + (tg >> 4)) * DM + 80 * hg + 8 * cq;
#pragma unroll
        for (int i = 0; i < 4; i++) stg128(dst + 2 * i * DM, make_uint4(u4(v[0], i), u4(v[1], i), u4(v[2], i), u4(v[3], i)));
    }
    if (bx == 0 && tid == 0) g_epoch = EPOCH + 1;
    TS(22);
    TS_END;
}
typedef CUresult (*EncodeTiledFn)(CUtensorMap*, CUtensorMapDataType, cuuint32_t, void*, const cuuint64_t*, const cuuint64_t*, const cuuint32_t*,
                                  const cuuint32_t*, CUtensorMapInterleave, CUtensorMapSwizzle, CUtensorMapL2promotion, CUtensorMapFloatOOBfill);

static void make_map(EncodeTiledFn enc, CUtensorMap* m, const void* base, int rank, const cuuint64_t* dims, const cuuint64_t* strides,
                     const cuuint32_t* box, CUtensorMapSwizzle sw) {
    cuuint32_t es[3] = {1, 1, 1};
    enc(m, CU_TENSOR_MAP_DATA_TYPE_BFLOAT16, rank, (void*)base, dims, strides, box, es, CU_TENSOR_MAP_INTERLEAVE_NONE, sw,
        sw == CU_TENSOR_MAP_SWIZZLE_128B ? CU_TENSOR_MAP_L2_PROMOTION_L2_128B : CU_TENSOR_MAP_L2_PROMOTION_NONE, CU_TENSOR_MAP_FLOAT_OOB_FILL_NONE);
}

template <typename... KArgs, typename... Args>
static void launch(void (*kern)(KArgs...), int grid, int block, int smem, int cluster, bool pdl, Args... args) {
    cudaLaunchConfig_t cfg = {};
    cfg.gridDim = dim3(grid); cfg.blockDim = dim3(block); cfg.dynamicSmemBytes = smem; cfg.stream = cudaStreamPerThread;
    cudaLaunchAttribute at[2];
    int n = 0;
    if (cluster > 1) { at[n].id = cudaLaunchAttributeClusterDimension; at[n].val.clusterDim.x = cluster; at[n].val.clusterDim.y = 1; at[n].val.clusterDim.z = 1; n++; }
    if (pdl) { at[n].id = cudaLaunchAttributeProgrammaticStreamSerialization; at[n].val.programmaticStreamSerializationAllowed = 1; n++; }
    cfg.attrs = at; cfg.numAttrs = n;
    cudaLaunchKernelEx(&cfg, kern, KArgs(args)...);
}

struct HostState {
    bool ready = false;
    const void* key[4] = {nullptr, nullptr, nullptr, nullptr};
    CUtensorMap mX[2], mRes[2], mW, mWr, mWo, mWor, mOut;
    bf16 *x1T, *x2T;
};

extern "C" void kernel_launch(void* const* d_in, const int* in_sizes, int n_in, void* d_out, int out_size) {
    const bf16* x = (const bf16*)d_in[0];
    const bf16* wqkv = (const bf16*)d_in[1];
    const bf16* wo = (const bf16*)d_in[2];
    const bf16* lar = (const bf16*)d_in[4];
    const bf16* aim = (const bf16*)d_in[5];
    const bf16* cre = (const bf16*)d_in[6];
    const bf16* cim = (const bf16*)d_in[7];
    const bf16* logdt = (const bf16*)d_in[8];
    const bf16* dskip = (const bf16*)d_in[9];
    static HostState hs;
    if (!hs.ready || hs.key[0] != wqkv || hs.key[1] != wo || hs.key[2] != x) {
        void* fn = nullptr;
        cudaDriverEntryPointQueryResult qr;
        cudaGetDriverEntryPoint("cuTensorMapEncodeTiled", &fn, cudaEnableDefault, &qr);
        EncodeTiledFn enc = (EncodeTiledFn)fn;
        cudaGetSymbolAddress((void**)&hs.x1T, g_x1T);
        cudaGetSymbolAddress((void**)&hs.x2T, g_x2T);
        {
            cuuint64_t d[3] = {DM, SEQ / 2, 2}, s[2] = {DM * 4, DM * 2};
            cuuint32_t b[3] = {64, 64, 2}, br[3] = {16, 64, 2};
            make_map(enc, &hs.mX[0], x, 3, d, s, b, CU_TENSOR_MAP_SWIZZLE_128B);
            make_map(enc, &hs.mRes[0], x, 3, d, s, br, CU_TENSOR_MAP_SWIZZLE_32B);
            cuuint64_t d2[3] = {SEQ / 2, DM, 2}, s2[2] = {XP * 2, SEQ};
            cuuint32_t b2[3] = {64, 80, 2};
            make_map(enc, &hs.mX[1], hs.x2T, 3, d2, s2, b, CU_TENSOR_MAP_SWIZZLE_128B);
            make_map(enc, &hs.mRes[1], hs.x2T, 3, d2, s2, b2, CU_TENSOR_MAP_SWIZZLE_128B);
            cuuint64_t d3[2] = {SEQ, DM};
            make_map(enc, &hs.mOut, hs.x1T, 2, d3, s2, b2, CU_TENSOR_MAP_SWIZZLE_128B);
        }
        { cuuint64_t d[2] = {3 * DM, DM}, s[1] = {3 * DM * 2}; cuuint32_t b[2] = {64, 32};
          make_map(enc, &hs.mW, wqkv, 2, d, s, b, CU_TENSOR_MAP_SWIZZLE_128B); }
        { cuuint64_t d[3] = {DM, DM, 3}, s[2] = {3 * DM * 2, DM * 2}; cuuint32_t b[3] = {16, 32, 3};
          make_map(enc, &hs.mWr, wqkv, 3, d, s, b, CU_TENSOR_MAP_SWIZZLE_32B); }
        { cuuint64_t d[2] = {DM, DM}, s[1] = {DM * 2}; cuuint32_t b[2] = {64, 40}, br[2] = {16, 40};
          make_map(enc, &hs.mWo, wo, 2, d, s, b, CU_TENSOR_MAP_SWIZZLE_128B);
          make_map(enc, &hs.mWor, wo, 2, d, s, br, CU_TENSOR_MAP_SWIZZLE_32B); }
        cudaFuncSetAttribute(fused_kernel, cudaFuncAttributeMaxDynamicSharedMemorySize, Q_SMEM);
        hs.key[0] = wqkv; hs.key[1] = wo; hs.key[2] = x;
        hs.ready = true;
    }
    const SsmParams sp = {lar, aim, cre, cim, logdt, dskip};
    launch(fused_kernel, 128, 384, Q_SMEM, 2, false, hs.mX[0], hs.mX[1], hs.mW, hs.mWr, hs.mWo, hs.mWor, hs.mRes[0], hs.mRes[1], hs.mOut, x, wqkv, wo, (bf16*)d_out, sp);
}
```

```cpp
#include <cuda_runtime.h>
#include <cuda.h>
#include <cuda_bf16.h>
#include <cuda_fp16.h>
#include <stdint.h>

typedef __nv_bfloat16 bf16;

constexpr int SEQ = 2048;
constexpr int DM  = 640;
constexpr int XP  = SEQ + 64;
constexpr int NMODE = 192;

__device__ __forceinline__ uint32_t s2u(const void* p) { return (uint32_t)__cvta_generic_to_shared(p); }
__device__ __forceinline__ void mbar_init(uint32_t b, int c) { asm volatile("mbarrier.init.shared::cta.b64 [%0], %1;" ::"r"(b), "r"(c)); }
__device__ __forceinline__ void mbar_expect(uint32_t b, uint32_t bytes) { asm volatile("mbarrier.arrive.expect_tx.shared::cta.b64 _, [%0], %1;" ::"r"(b), "r"(bytes) : "memory"); }
__device__ __forceinline__ void mbar_arrive(uint32_t b) { asm volatile("mbarrier.arrive.shared::cta.b64 _, [%0];" ::"r"(b) : "memory"); }
__device__ __forceinline__ void mbar_arrive_cta(uint32_t b, uint32_t cta) {
    asm volatile("{\n.reg .b32 ra;\nmapa.shared::cluster.u32 ra, %0, %1;\nmbarrier.arrive.shared::cluster.b64 _, [ra];\n}" ::"r"(b), "r"(cta) : "memory");
}
__device__ __forceinline__ void mbar_wait(uint32_t b, uint32_t ph) {
    asm volatile("{\n.reg .pred p;\n.reg .u32 n;\nmbarrier.try_wait.parity.shared::cta.b64 p, [%0], %1;\n@p bra D;\nmov.u32 n, 0;\n"
                 "W: mbarrier.try_wait.parity.shared::cta.b64 p, [%0], %1;\n@p bra D;\nadd.u32 n, n, 1;\nsetp.lt.u32 p, n, 4194304;\n@p bra W;\ntrap;\nD:\n}"
                 ::"r"(b), "r"(ph) : "memory");
}
__device__ __forceinline__ void fence_mbar_init() { asm volatile("fence.mbarrier_init.release.cluster;" ::: "memory"); }
__device__ __forceinline__ void cluster_sync() { asm volatile("barrier.cluster.arrive.aligned;\nbarrier.cluster.wait.aligned;" ::: "memory"); }
__device__ __forceinline__ void pdl_wait() { asm volatile("griddepcontrol.wait;" ::: "memory"); }
__device__ __forceinline__ void pdl_launch() { asm volatile("griddepcontrol.launch_dependents;" ::: "memory"); }
__device__ __forceinline__ void named_bar(int id, int n) { asm volatile("bar.sync %0, %1;" ::"r"(id), "r"(n) : "memory"); }
__device__ __forceinline__ void fence_async_smem() { asm volatile("fence.proxy.async.shared::cta;" ::: "memory"); }

__device__ __forceinline__ void tma2d(uint32_t dst, const CUtensorMap* m, int c0, int c1, uint32_t bar) {
    asm volatile("cp.async.bulk.tensor.2d.shared::cluster.global.mbarrier::complete_tx::bytes [%0], [%1, {%3, %4}], [%2];"
                 ::"r"(dst), "l"(m), "r"(bar), "r"(c0), "r"(c1) : "memory");
}
__device__ __forceinline__ void tma2d_mc(uint32_t dst, const CUtensorMap* m, int c0, int c1, uint32_t bar, uint16_t mask) {
    asm volatile("cp.async.bulk.tensor.2d.shared::cluster.global.mbarrier::complete_tx::bytes.multicast::cluster [%0], [%1, {%3, %4}], [%2], %5;"
                 ::"r"(dst), "l"(m), "r"(bar), "r"(c0), "r"(c1), "h"(mask) : "memory");
}
__device__ __forceinline__ void tma3d(uint32_t dst, const CUtensorMap* m, int c0, int c1, int c2, uint32_t bar) {
    asm volatile("cp.async.bulk.tensor.3d.shared::cluster.global.mbarrier::complete_tx::bytes [%0], [%1, {%3, %4, %5}], [%2];"
                 ::"r"(dst), "l"(m), "r"(bar), "r"(c0), "r"(c1), "r"(c2) : "memory");
}
__device__ __forceinline__ void tma3d_mc(uint32_t dst, const CUtensorMap* m, int c0, int c1, int c2, uint32_t bar, uint16_t mask) {
    asm volatile("cp.async.bulk.tensor.3d.shared::cluster.global.mbarrier::complete_tx::bytes.multicast::cluster [%0], [%1, {%3, %4, %5}], [%2], %6;"
                 ::"r"(dst), "l"(m), "r"(bar), "r"(c0), "r"(c1), "r"(c2), "h"(mask) : "memory");
}
__device__ __forceinline__ void bulk_g2s(uint32_t dst, const void* src, uint32_t bytes, uint32_t bar) {
    asm volatile("cp.async.bulk.shared::cluster.global.mbarrier::complete_tx::bytes [%0], [%1], %2, [%3];"
                 ::"r"(dst), "l"(src), "r"(bytes), "r"(bar) : "memory");
}
__device__ __forceinline__ void bulk_g2s_mc(uint32_t dst, const void* src, uint32_t bytes, uint32_t bar, uint16_t mask) {
    asm volatile("cp.async.bulk.shared::cluster.global.mbarrier::complete_tx::bytes.multicast::cluster [%0], [%1], %2, [%3], %4;"
                 ::"r"(dst), "l"(src), "r"(bytes), "r"(bar), "h"(mask) : "memory");
}
__device__ __forceinline__ void prefetch_l2(const void* p, uint32_t bytes) { asm volatile("cp.async.bulk.prefetch.L2.global [%0], %1;" ::"l"(p), "r"(bytes) : "memory"); }
__device__ __forceinline__ void prefetch_tmap(const CUtensorMap* m) { asm volatile("prefetch.tensormap [%0];" ::"l"(m) : "memory"); }

__device__ __forceinline__ void wg_fence() { asm volatile("wgmma.fence.sync.aligned;" ::: "memory"); }
__device__ __forceinline__ void wg_commit() { asm volatile("wgmma.commit_group.sync.aligned;" ::: "memory"); }
template <int N> __device__ __forceinline__ void wg_wait() { asm volatile("wgmma.wait_group.sync.aligned %0;" ::"n"(N) : "memory"); }
__device__ __forceinline__ uint64_t mkdesc(uint32_t addr, uint32_t lbo, uint32_t sbo, uint32_t mode) {
    return (uint64_t)((addr & 0x3FFFF) >> 4) | ((uint64_t)(lbo >> 4) << 16) | ((uint64_t)(sbo >> 4) << 32) | ((uint64_t)mode << 62);
}

__device__ __forceinline__ void mma16816(float (&c)[4], uint32_t a0, uint32_t a1, uint32_t a2, uint32_t a3, uint32_t b0, uint32_t b1) {
    asm("mma.sync.aligned.m16n8k16.row.col.f32.bf16.bf16.f32 {%0,%1,%2,%3},{%4,%5,%6,%7},{%8,%9},{%0,%1,%2,%3};"
                 : "+f"(c[0]), "+f"(c[1]), "+f"(c[2]), "+f"(c[3]) : "r"(a0), "r"(a1), "r"(a2), "r"(a3), "r"(b0), "r"(b1));
}
__device__ __forceinline__ void mma1688(float (&c)[4], uint32_t a0, uint32_t a1, uint32_t b0) {
    asm("mma.sync.aligned.m16n8k8.row.col.f32.bf16.bf16.f32 {%0,%1,%2,%3},{%4,%5},{%6},{%0,%1,%2,%3};"
                 : "+f"(c[0]), "+f"(c[1]), "+f"(c[2]), "+f"(c[3]) : "r"(a0), "r"(a1), "r"(b0));
}
__device__ __forceinline__ void ldsm_x4(uint32_t& r0, uint32_t& r1, uint32_t& r2, uint32_t& r3, uint32_t a) {
    asm volatile("ldmatrix.sync.aligned.m8n8.x4.shared.b16 {%0,%1,%2,%3}, [%4];" : "=r"(r0), "=r"(r1), "=r"(r2), "=r"(r3) : "r"(a) : "memory");
}
__device__ __forceinline__ void ldsm_x4_t(uint32_t& r0, uint32_t& r1, uint32_t& r2, uint32_t& r3, uint32_t a) {
    asm volatile("ldmatrix.sync.aligned.m8n8.x4.trans.shared.b16 {%0,%1,%2,%3}, [%4];" : "=r"(r0), "=r"(r1), "=r"(r2), "=r"(r3) : "r"(a) : "memory");
}
__device__ __forceinline__ void ldsm_x2(uint32_t& r0, uint32_t& r1, uint32_t a) {
    asm volatile("ldmatrix.sync.aligned.m8n8.x2.shared.b16 {%0,%1}, [%2];" : "=r"(r0), "=r"(r1) : "r"(a) : "memory");
}
__device__ __forceinline__ void ldsm_x2_t(uint32_t& r0, uint32_t& r1, uint32_t a) {
    asm volatile("ldmatrix.sync.aligned.m8n8.x2.trans.shared.b16 {%0,%1}, [%2];" : "=r"(r0), "=r"(r1) : "r"(a) : "memory");
}
__device__ __forceinline__ void stsm_x4(uint32_t a, uint32_t r0, uint32_t r1, uint32_t r2, uint32_t r3) {
    asm volatile("stmatrix.sync.aligned.m8n8.x4.shared.b16 [%0], {%1,%2,%3,%4};" ::"r"(a), "r"(r0), "r"(r1), "r"(r2), "r"(r3) : "memory");
}
__device__ __forceinline__ void stsm_x4_t(uint32_t a, uint32_t r0, uint32_t r1, uint32_t r2, uint32_t r3) {
    asm volatile("stmatrix.sync.aligned.m8n8.x4.trans.shared.b16 [%0], {%1,%2,%3,%4};" ::"r"(a), "r"(r0), "r"(r1), "r"(r2), "r"(r3) : "memory");
}
__device__ __forceinline__ void stsm_x2(uint32_t a, uint32_t r0, uint32_t r1) {
    asm volatile("stmatrix.sync.aligned.m8n8.x2.shared.b16 [%0], {%1,%2};" ::"r"(a), "r"(r0), "r"(r1) : "memory");
}
__device__ __forceinline__ uint32_t movm_t(uint32_t a) {
    uint32_t d;
    asm volatile("movmatrix.sync.aligned.m8n8.trans.b16 %0, %1;" : "=r"(d) : "r"(a));
    return d;
}
__device__ __forceinline__ uint32_t lds32(uint32_t a) { uint32_t v; asm volatile("ld.shared.u32 %0, [%1];" : "=r"(v) : "r"(a) : "memory"); return v; }
__device__ __forceinline__ uint32_t ldsv32(uint32_t a) { uint32_t v; asm volatile("ld.volatile.shared.u32 %0, [%1];" : "=r"(v) : "r"(a) : "memory"); return v; }
__device__ __forceinline__ void sts32(uint32_t a, uint32_t v) { asm volatile("st.shared.u32 [%0], %1;" ::"r"(a), "r"(v) : "memory"); }
__device__ __forceinline__ uint4 lds128(uint32_t a) { uint4 v; asm volatile("ld.shared.v4.u32 {%0,%1,%2,%3}, [%4];" : "=r"(v.x), "=r"(v.y), "=r"(v.z), "=r"(v.w) : "r"(a) : "memory"); return v; }
__device__ __forceinline__ void sts128(uint32_t a, uint4 v) { asm volatile("st.shared.v4.u32 [%0], {%1,%2,%3,%4};" ::"r"(a), "r"(v.x), "r"(v.y), "r"(v.z), "r"(v.w) : "memory"); }

__device__ __forceinline__ void stg128(void* p, uint4 v) { asm volatile("st.global.v4.u32 [%0], {%1,%2,%3,%4};" ::"l"(p), "r"(v.x), "r"(v.y), "r"(v.z), "r"(v.w) : "memory"); }

__device__ __forceinline__ uint4 ldg128(const void* p) { uint4 v; asm volatile("ld.global.v4.u32 {%0,%1,%2,%3}, [%4];" : "=r"(v.x), "=r"(v.y), "=r"(v.z), "=r"(v.w) : "l"(p) : "memory"); return v; }
__device__ __forceinline__ uint2 ldg64(const void* p) { uint2 v; asm volatile("ld.global.v2.u32 {%0,%1}, [%2];" : "=r"(v.x), "=r"(v.y) : "l"(p) : "memory"); return v; }
__device__ __forceinline__ uint32_t ldg32(const void* p) { uint32_t v; asm volatile("ld.global.u32 %0, [%1];" : "=r"(v) : "l"(p) : "memory"); return v; }

__device__ __forceinline__ uint32_t pack2(float lo, float hi) {
    uint32_t r;
    asm("cvt.rn.bf16x2.f32 %0, %1, %2;" : "=r"(r) : "f"(hi), "f"(lo));
    return r;
}
__device__ __forceinline__ float bf_lo(uint32_t v) { return __uint_as_float(v << 16); }
__device__ __forceinline__ float bf_hi(uint32_t v) { return __uint_as_float(v & 0xFFFF0000u); }
__device__ __forceinline__ float rbf(float x) { return __uint_as_float(pack2(0.f, x) & 0xFFFF0000u); }
__device__ __forceinline__ float ex2(float x) { float r; asm("ex2.approx.ftz.f32 %0, %1;" : "=f"(r) : "f"(x)); return r; }

__device__ __forceinline__ float2 ln_finish(float sum, float sumsq) {
    const float m = sum * (1.0f / DM);
    const float v = fmaxf(fmaf(sumsq, 1.0f / DM, -m * m), 0.f);
    float s, r;
    asm("sqrt.approx.ftz.f32 %0, %1;" : "=f"(s) : "f"(rbf(rbf(v) + 1e-5f)));
    asm("rcp.approx.ftz.f32 %0, %1;" : "=f"(r) : "f"(rbf(s)));
    return make_float2(m, r);
}
__device__ __forceinline__ uint32_t ln_finish_packed(float sum, float sumsq) {
    const float m = sum * (1.0f / DM);
    const float v = fmaxf(fmaf(sumsq, 1.0f / DM, -m * m), 0.f);
    float s;
    asm("sqrt.approx.ftz.f32 %0, %1;" : "=f"(s) : "f"(rbf(rbf(v) + 1e-5f)));
    return pack2(s, m);
}
__device__ __forceinline__ float frsq(float x) { float r; asm("rsqrt.approx.ftz.f32 %0, %1;" : "=f"(r) : "f"(x)); return r; }
__device__ __forceinline__ float frcp(float x) { float r; asm("rcp.approx.ftz.f32 %0, %1;" : "=f"(r) : "f"(x)); return r; }
__device__ __forceinline__ bool elect_one() {
    uint32_t p;
    asm volatile("{\n.reg .pred p;\nelect.sync _|p, 0xffffffff;\nselp.u32 %0, 1, 0, p;\n}" : "=r"(p));
    return p != 0;
}
__device__ __forceinline__ void cluster_arrive_relaxed() { asm volatile("barrier.cluster.arrive.relaxed.aligned;" ::: "memory"); }
__device__ __forceinline__ void cluster_wait() { asm volatile("barrier.cluster.wait.aligned;" ::: "memory"); }
__device__ __forceinline__ unsigned long long ld_ll(const unsigned long long* p) {
    unsigned long long v;
    asm volatile("ld.relaxed.gpu.global.b64 %0, [%1];" : "=l"(v) : "l"(p) : "memory");
    return v;
}
__device__ __forceinline__ void st_ll(unsigned long long* p, uint32_t payload, uint32_t tag) {
    const unsigned long long v = (unsigned long long)payload | ((unsigned long long)tag << 32);
    asm volatile("st.relaxed.gpu.global.b64 [%0], %1;" ::"l"(p), "l"(v) : "memory");
}
__device__ __forceinline__ uint4 ld_ll4(const uint4* p) {
    uint4 v;
    asm volatile("{\n.reg .b128 t;\n.reg .b64 a, b;\nld.relaxed.gpu.global.b128 t, [%4];\nmov.b128 {a, b}, t;\nmov.b64 {%0, %1}, a;\nmov.b64 {%2, %3}, b;\n}"
                 : "=r"(v.x), "=r"(v.y), "=r"(v.z), "=r"(v.w) : "l"(p) : "memory");
    return v;
}
__device__ __forceinline__ void st_ll4(uint4* p, uint32_t x, uint32_t y, uint32_t z, uint32_t w) {
    asm volatile("{\n.reg .b128 t;\n.reg .b64 a, b;\nmov.b64 a, {%1, %2};\nmov.b64 b, {%3, %4};\nmov.b128 t, {a, b};\nst.relaxed.gpu.global.b128 [%0], t;\n}"
                 ::"l"(p), "r"(x), "r"(y), "r"(z), "r"(w) : "memory");
}

__device__ __forceinline__ void bulk_s2g(void* dst, uint32_t src, uint32_t bytes) {
    asm volatile("cp.async.bulk.global.shared::cta.bulk_group [%0], [%1], %2;" ::"l"(dst), "r"(src), "r"(bytes) : "memory");
}
__device__ __forceinline__ void bulk_commit() { asm volatile("cp.async.bulk.commit_group;" ::: "memory"); }
__device__ __forceinline__ void bulk_wait() { asm volatile("cp.async.bulk.wait_group 0;" ::: "memory"); }
__device__ __forceinline__ void fence_async_global() { asm volatile("fence.proxy.async.global;" ::: "memory"); }
__device__ __forceinline__ void fence_release() { asm volatile("fence.release.gpu;" ::: "memory"); }
__device__ __forceinline__ void fence_acquire() { asm volatile("fence.acquire.gpu;" ::: "memory"); }
template<int TA, int TB>
__device__ __forceinline__ void wgmma_n192(float (&d)[96], uint64_t da, uint64_t db, int scale_d) {
  asm volatile("{\n.reg .pred p;\nsetp.ne.b32 p, %98, 0;\n"
    "wgmma.mma_async.sync.aligned.m64n192k16.f32.bf16.bf16 "
    "{%0, %1, %2, %3, %4, %5, %6, %7, %8, %9, %10, %11, %12, %13, %14, %15, %16, %17, %18, %19, %20, %21, %22, %23, %24, %25, %26, %27, %28, %29, %30, %31, %32, %33, %34, %35, %36, %37, %38, %39, %40, %41, %42, %43, %44, %45, %46, %47, %48, %49, %50, %51, %52, %53, %54, %55, %56, %57, %58, %59, %60, %61, %62, %63, %64, %65, %66, %67, %68, %69, %70, %71, %72, %73, %74, %75, %76, %77, %78, %79, %80, %81, %82, %83, %84, %85, %86, %87, %88, %89, %90, %91, %92, %93, %94, %95}, %96, %97, p, 1, 1, %99, %100;\n}\n"
    : "+f"(d[0]), "+f"(d[1]), "+f"(d[2]), "+f"(d[3]), "+f"(d[4]), "+f"(d[5]), "+f"(d[6]), "+f"(d[7]), "+f"(d[8]), "+f"(d[9]), "+f"(d[10]), "+f"(d[11]), "+f"(d[12]), "+f"(d[13]), "+f"(d[14]), "+f"(d[15]), "+f"(d[16]), "+f"(d[17]), "+f"(d[18]), "+f"(d[19]), "+f"(d[20]), "+f"(d[21]), "+f"(d[22]), "+f"(d[23]), "+f"(d[24]), "+f"(d[25]), "+f"(d[26]), "+f"(d[27]), "+f"(d[28]), "+f"(d[29]), "+f"(d[30]), "+f"(d[31]), "+f"(d[32]), "+f"(d[33]), "+f"(d[34]), "+f"(d[35]), "+f"(d[36]), "+f"(d[37]), "+f"(d[38]), "+f"(d[39]), "+f"(d[40]), "+f"(d[41]), "+f"(d[42]), "+f"(d[43]), "+f"(d[44]), "+f"(d[45]), "+f"(d[46]), "+f"(d[47]), "+f"(d[48]), "+f"(d[49]), "+f"(d[50]), "+f"(d[51]), "+f"(d[52]), "+f"(d[53]), "+f"(d[54]), "+f"(d[55]), "+f"(d[56]), "+f"(d[57]), "+f"(d[58]), "+f"(d[59]), "+f"(d[60]), "+f"(d[61]), "+f"(d[62]), "+f"(d[63]), "+f"(d[64]), "+f"(d[65]), "+f"(d[66]), "+f"(d[67]), "+f"(d[68]), "+f"(d[69]), "+f"(d[70]), "+f"(d[71]), "+f"(d[72]), "+f"(d[73]), "+f"(d[74]), "+f"(d[75]), "+f"(d[76]), "+f"(d[77]), "+f"(d[78]), "+f"(d[79]), "+f"(d[80]), "+f"(d[81]), "+f"(d[82]), "+f"(d[83]), "+f"(d[84]), "+f"(d[85]), "+f"(d[86]), "+f"(d[87]), "+f"(d[88]), "+f"(d[89]), "+f"(d[90]), "+f"(d[91]), "+f"(d[92]), "+f"(d[93]), "+f"(d[94]), "+f"(d[95])
    : "l"(da), "l"(db), "r"(scale_d), "n"(TA), "n"(TB));
}

template<int TA, int TB>
__device__ __forceinline__ void wgmma_n48(float (&d)[24], uint64_t da, uint64_t db, int scale_d) {
  asm volatile("{\n.reg .pred p;\nsetp.ne.b32 p, %26, 0;\n"
    "wgmma.mma_async.sync.aligned.m64n48k16.f32.bf16.bf16 "
    "{%0, %1, %2, %3, %4, %5, %6, %7, %8, %9, %10, %11, %12, %13, %14, %15, %16, %17, %18, %19, %20, %21, %22, %23}, %24, %25, p, 1, 1, %27, %28;\n}\n"
    : "+f"(d[0]), "+f"(d[1]), "+f"(d[2]), "+f"(d[3]), "+f"(d[4]), "+f"(d[5]), "+f"(d[6]), "+f"(d[7]), "+f"(d[8]), "+f"(d[9]), "+f"(d[10]), "+f"(d[11]), "+f"(d[12]), "+f"(d[13]), "+f"(d[14]), "+f"(d[15]), "+f"(d[16]), "+f"(d[17]), "+f"(d[18]), "+f"(d[19]), "+f"(d[20]), "+f"(d[21]), "+f"(d[22]), "+f"(d[23])
    : "l"(da), "l"(db), "r"(scale_d), "n"(TA), "n"(TB));
}

__device__ __forceinline__ void wgmma_rs80(float (&d)[40], const uint4& a, uint64_t db, int scale_d) {
  asm volatile("{\n.reg .pred p;\nsetp.ne.b32 p, %45, 0;\n"
    "wgmma.mma_async.sync.aligned.m64n80k16.f32.bf16.bf16 {%0,%1,%2,%3,%4,%5,%6,%7,%8,%9,%10,%11,%12,%13,%14,%15,%16,%17,%18,%19,%20,%21,%22,%23,%24,%25,%26,%27,%28,%29,%30,%31,%32,%33,%34,%35,%36,%37,%38,%39}, {%40,%41,%42,%43}, %44, p, 1, 1, 1;\n}\n"
    : "+f"(d[0]), "+f"(d[1]), "+f"(d[2]), "+f"(d[3]), "+f"(d[4]), "+f"(d[5]), "+f"(d[6]), "+f"(d[7]), "+f"(d[8]), "+f"(d[9]), "+f"(d[10]), "+f"(d[11]), "+f"(d[12]), "+f"(d[13]), "+f"(d[14]), "+f"(d[15]), "+f"(d[16]), "+f"(d[17]), "+f"(d[18]), "+f"(d[19]), "+f"(d[20]), "+f"(d[21]), "+f"(d[22]), "+f"(d[23]), "+f"(d[24]), "+f"(d[25]), "+f"(d[26]), "+f"(d[27]), "+f"(d[28]), "+f"(d[29]), "+f"(d[30]), "+f"(d[31]), "+f"(d[32]), "+f"(d[33]), "+f"(d[34]), "+f"(d[35]), "+f"(d[36]), "+f"(d[37]), "+f"(d[38]), "+f"(d[39])
    : "r"(a.x), "r"(a.y), "r"(a.z), "r"(a.w), "l"(db), "r"(scale_d));
}

__device__ const __align__(1024) uint32_t c_fft[11264] = {
0x2ddc2dba,0x2fe62eb5,0x2ed02eb5,0xafffaf6e,0x2e1f2dfe,0x2e3f2fbc,0x2f022ee9,0xad27af30,0x2e5e2e3f,0x1fd92b5e,0x2f302f1a,0x244ea875,0x2e992e7c,0xad96a993,0x2f5a2f46,0x2e992c32,
0xad00ad72,0xa17eac32,0xa17ea515,0xabb79cb6,0xac07ac87,0x2dfe29f1,0x1fd99648,0xafedae99,0xa9f1ab05,0x2fd42fbc,0x26a1244e,0xad96af91,0xa765a8d5,0x2aaa2e3f,0x29932875,0x2515a8d5,
0xae99adfe,0xb000aee9,0xaf6eafbc,0x2c872f30,0xaf80af1a,0xac32af02,0xae7caf02,0xaaaa217e,0xaff4afc9,0x2b5e9cb6,0xad27addc,0xaff4ae7c,0xafedb000,0x2ffc2eb5,0xab05ac5d,0xacd8af5a,
0x2c072d27,0x9fd92bb7,0xadfead00,0x2fed2e1f,0x25db2993,0xaf6eacb0,0xaf6eaed0,0x2c5d2f46,0xa5151648,0xaddcafdd,0xafffafd4,0xac321648,0xabb7a934,0x28d5a814,0xafa0afed,0xaff4af30,
0x2f302e3f,0x2fed2f1a,0x28142b5e,0x2934a875,0x30002fc9,0x26a12ddc,0xa5db1cb6,0x30002e7c,0x2f462fd4,0xaed0aa4e,0xacb0aa4e,0x29932e99,0x2d272e5e,0xae3faffc,0xaf02adfe,0xae1fa814,
0xa9f1acd8,0x26a1ab05,0x2fd42ffc,0xad96afed,0x2515a30e,0x2fff2e1f,0x2ddc2f1a,0x2c32a30e,0x2d272aaa,0x28752e7c,0x28752c32,0x2fa02f80,0x2f912e99,0xaee9a9f1,0xa8141648,0x9fd92c87,
0xafa0ae7c,0xafafaf46,0x2d002993,0xafa0ac32,0xaf91b000,0x244eac5d,0x2fbc2eb5,0xab05af5a,0xac87ae5e,0x30002dfe,0x2f6e2ffc,0x2e992814,0x1cb6a875,0x25152e1f,0x2c322e1f,0x2d722ff4,
0x27652c87,0xa9932a4e,0xaaaaadba,0xa5152c87,0xabb7a44e,0xafa0af30,0x28d59fd9,0xaff4ae5e,0xaf91ae1f,0x2814abb7,0x2ee92d00,0x1fd9ad27,0xaf5aafff,0x2fd42ed0,0x2fd42fe6,0x30002ddc,
0x2f462f6e,0x2c322fdd,0x2e7c2fdd,0xa993b000,0xab5e2934,0xafafacd8,0xad00244e,0x2f1a2dfe,0xaee9afaf,0x2f30a17e,0xadfeaff8,0xafbca30e,0x2c5da765,0xa9f12ddc,0x2d969cb6,0x2c5dacb0,
0x2bb7a993,0x2f1aa515,0x2f1a2765,0xaff4aaaa,0x2e5e2fd4,0xab052dba,0x29342f6e,0x2ee9a6a1,0xadba1fd9,0xa5dbafed,0xafddac07,0xaa4e2dfe,0xacb0aff8,0x2ddc2f02,0x9cb6ae3f,0xa765aff8,
0xaeb5af91,0xaa4eafed,0x9648ae5e,0xac5d2d4d,0x2ddca17e,0x2e7c2e3f,0x2fc92e3f,0x1cb6afa0,0x2bb72fe6,0xaff8a993,0xab5e2aaa,0x2bb72fc9,0xafbcaa4e,0x2f30a5db,0xadfeafdd,0xaee9adba,
0xacd828d5,0xaf91230e,0xaf30af02,0x2c072fa0,0xac5dafff,0x2dbaac32,0x2dbaa515,0xae99addc,0x2fc929f1,0xa9932eb5,0x2aaa2fdd,0x2fe629f1,0xa30e2dfe,0xa17eafed,0xaff8ac07,0xafaf1fd9,
0x2dfe2faf,0x28142ff8,0xae5e217e,0x2ffc230e,0xaf5aa515,0xac87af46,0xa6a1af80,0xaf5a2765,0x1cb6ae99,0x2e7c2dba,0x2fc92dba,0x2ddcac5d,0x2f1a2ee9,0xafafab05,0xad002934,0xab5e2e5e,
0x2dbaa814,0x2fdd9fd9,0x25db2f91,0x2a4eaee9,0x27652faf,0xaf4628d5,0xaf80ae1f,0xa5152faf,0xafa0addc,0x2e3fac32,0x2e3fa515,0xa17eafff,0x2dfea6a1,0xacd82dba,0x244e2f6e,0x29342fd4,
0xad27afc9,0xa30eafff,0x2faf2d72,0xad27ae7c,0x2ffc2a4e,0x28142fdd,0xae5e25db,0x2dfe2dba,0xac5d2c07,0xaa4eaf91,0x9648af30,0xaeb5acd8,0xa993aff4,0x2c322f1a,0x2e7c2f1a,0x2f462bb7,
0xae7c26a1,0xafff1648,0x2d72aa4e,0xafc926a1,0x230eaee9,0x2ff89fd9,0x217e2f91,0x2fafa814,0x2d4d2fa0,0xafed230e,0xae5eaf02,0xaf9128d5,0xb000aaaa,0x2fdda515,0x2fdd2765,0x2f6ea993,
0x9cb63000,0xacb02fd4,0xa7652fd4,0x2ddcaf5a,0x217eaffc,0x2ff4ac07,0x2875afbc,0xaff82934,0xa44e2ff4,0xadfea8d5,0xa9342fa0,0x2cd82bb7,0x25dbafe6,0x16482f46,0x29f1af80,0x25dbafc9,
0x2ff41cb6,0x2e1f2765,0x2e1f2cb0,0xa875addc,0xafbca5db,0x1fd9af5a,0xad4dad96,0xacd82fdd,0x2f5a2934,0xaeb52ee9,0x2c5d2e5e,0x3000ab05,0xaed0ab5e,0x2f80a30e,0xaaaaaf02,0xacb0ab5e,
0x25dbaffc,0x2d96afbc,0x2f5aac07,0xafdd2934,0xaaaa2fa0,0xafc92875,0xafe62875,0x29932d27,0x2d00aed0,0x28d52d72,0x2ff89cb6,0x2d00afe6,0xae5e2d96,0x2d4dafd4,0xaf91a6a1,0xafed29f1,
0xafbca17e,0xad4da875,0x1fd9aff4,0xacd82ff8,0x2e992aaa,0xaa4e2fe6,0xaa4e2fc9,0x2fd4a993,0xacb0ad96,0x2fffac87,0x2d72aeb5,0xa765ad96,0x28752f30,0xab5eac07,0xaf1a2cd8,0xae3f2f91,
0xa9342ff4,0xae5e2fa0,0xaee9a8d5,0x2b052bb7,0x2d96aed0,0x2eb59cb6,0x2c872d72,0x2d96afe6,0xaf802c5d,0x2765af6e,0xa515af6e,0xaf4625db,0x2ff8a44e,0xaff42d4d,0xa8752ffc,0xa17e2ee9,
0x2f5a244e,0x2c5d2934,0xaeb52dfe,0x3000acd8,0xacb0ad00,0x2d72aff8,0x2fffa8d5,0xa765ad00,0x217e2f80,0xaf022515,0xaf02a765,0xaf1a2f46,0x2b05afdd,0xa8142f5a,0x2c072d96,0x2d4d25db,
0x2b5eafe6,0x2f02af80,0x230e2f46,0x2b5eafc9,0xaf302d96,0xacd8a6a1,0x2c07afd4,0xaf9129f1,0x2fdda44e,0xad962ffc,0xaf5a2d4d,0xa5db2ee9,0xad72abb7,0x2e7ca17e,0x2fc9a17e,0x2fffad00,
0xaed0a5db,0xaaaaa9f1,0x2f809648,0xacb0a5db,0x28752e5e,0xaf1a2f91,0xab5ead4d,0xae3f2fed,0x2b05aff8,0x2c072875,0xa8142ff4,0x2d4d217e,0xaf6e2d72,0x2eb5afc9,0x2eb5ae7c,0x2dbaafff,
0xaf802f5a,0xafc92e99,0xafe62e99,0x2f46ad96,0x28d52b05,0xaf022fed,0x230e2cd8,0x2fa0affc,0x2fbcaf02,0xa9342d27,0x2ffcae1f,0x2c07ae3f,0xa6a1ac32,0x2a4e9cb6,0x9648ad72,0xa6a1a515,
0x28752aaa,0xa8d52cb0,0xa8d52ed0,0x2e3faf80,0x2fedaeb5,0x29349648,0x2f30aa4e,0x2814ac5d,0x1648ad4d,0x2e99acd8,0x2c87afbc,0xa9f11fd9,0xafe62d27,0x2fffafaf,0xaddc230e,0xaed02d27,
0x2fd4af30,0x2f6eae5e,0x2dbaa44e,0xa6a19fd9,0x1cb6ad27,0x2fe6aff4,0x2ed0aff4,0xad722b5e,0xafaf2cb0,0x2e1faf46,0xa8d5a993,0xafaf2ed0,0xac072f6e,0x2934ac87,0xaffc2e99,0xafbc3000,
0xa44eab5e,0x2b05ad00,0x2f91afaf,0xafbc2f1a,0xafd42d72,0x1648a765,0x1648acb0,0xafdd2fff,0xac322f5a,0xaaaa26a1,0xaf802c87,0xae7c2f5a,0x2d009fd9,0xae1f2cd8,0xad272fbc,0xabb72d4d,
0xaffc2f02,0xaee92e1f,0x244ead27,0xad4d2e3f,0xa9f12e7c,0xafdd2f80,0xaeb52aaa,0xa9f12c32,0x2d72a5db,0xafe63000,0xaed03000,0x9cb626a1,0x2fa0afbc,0xaf022f91,0x230e2b05,0x28d5a44e,
0x96482c07,0xac872d4d,0xae992b05,0x29f1a814,0x2ed0abb7,0xa9932b5e,0xaf462ff8,0x2cb0abb7,0x2f1aafff,0xa30e2765,0xa30e2cb0,0x2e1fad72,0x1fd9ac5d,0x244e9648,0x2e5eaa4e,0x2f30aeb5,
0x2ff8aed0,0x2e3faddc,0xaf022fff,0x2ff8afe6,0x2d4daf6e,0x2ee9ae99,0xa44e2c87,0x2ffcb000,0xa6a1a814,0x2f6eaf30,0x2dbaa934,0x2fd4afed,0xaf462d00,0x2fc9afa0,0x2fe6afa0,0x2f80afaf,
0x2515ac5d,0x2d72ad96,0x1cb629f1,0x2c32ac5d,0xad002814,0x2d27ad4d,0x2e1fab05,0x2bb7ac07,0xaffc2f1a,0x2cd8ad00,0x2fedafaf,0x2b05ab5e,0xadba2f80,0x2c87acb0,0x2c87aed0,0x2a4eaaaa,
0x2f802f6e,0x2fc92fdd,0x2fe62fdd,0xaf46b000,0x2fa02f91,0x2bb72e5e,0x2ff42fed,0xa8d5ad4d,0x2fbc2faf,0xa934217e,0x2ffc2ff8,0x2c07230e,0x2fd42fc9,0xaf5aad72,0x30002fff,0x2fd42e7c,
0x2bb72aaa,0x2f1a2cb0,0x2f1a2ed0,0xaff4af80,0x2cd82c5d,0x2f303000,0x2f912f5a,0xac07aeb5,0x2dba2d4d,0x25db2cd8,0x2fdd2fbc,0x2a4e9fd9,0x2e7c2e1f,0xad72a875,0x2fff2ff4,0x2fc92e1f,
0xa6a1a934,0x29f1a44e,0x2d962cd8,0xafd4adfe,0x1cb6a17e,0x2fe62e3f,0x2ed02e3f,0xad72afa0,0x28752515,0x2d272f80,0x2fa02f46,0x2875a765,0x2c072a4e,0xa93425db,0x2ffc2fdd,0x2fbc2dba,
0xae5eaf1a,0xa934ae3f,0x2b052875,0xaee9ab5e,0xac5dad72,0x2dba2765,0x2dba2cb0,0xae99afff,0xa765aa4e,0x2f802fd4,0x2f462e99,0x2515aa4e,0x230e9fd9,0x217e2cd8,0x2ff82fbc,0x2faf2d4d,
0xaffcafaf,0xaee9aff8,0x244ea17e,0xad4da30e,0xaf6eafe6,0x25dbaaaa,0x2c5d2993,0xaf6eafc9,0xad72ae99,0x2fe62dba,0x2ed02dba,0x1cb6ac5d,0xa8d5ac07,0x2bb72f30,0x2ff42f91,0x2fa02cd8,
0xadbaac07,0xafddad4d,0xa5dbab05,0xaa4e2814,0xafc9af02,0xaaaaaf1a,0x2993217e,0xafe6af02,0xafa0afff,0x2e3f2765,0x2e3f2cb0,0xa17ead72,0xad4daeb5,0x2e5e3000,0x2fed2f5a,0x2f912c5d,
0xa17e2765,0xad001cb6,0xabb7addc,0xa17e2cb0,0xad4daa4e,0xaee9afdd,0x244ea5db,0xaffcadba,0xafd4aee9,0x29f1a934,0x2d962b05,0xa6a1ae5e,0xaf46aff4,0x2fc92f1a,0x2fe62f1a,0x2f802bb7,
0x2cb02eb5,0x1cb62dba,0xaddcaf6e,0x27652eb5,0xa30e2814,0xaff8ad4d,0xa17eab05,0xafafac07,0xadfeab5e,0xa44eae3f,0x2cd82875,0xa934af1a,0xb000af80,0x2fdd2cb0,0x2fdd2ed0,0x2f6e2aaa,
0x2d723000,0x25152fd4,0x2c322fd4,0x1cb6af5a,0xae1f9fd9,0xae3faee9,0xaf02a814,0x2d272f91,0xacd8aff4,0x2ffc28d5,0xab05afa0,0xafedabb7,0x2e992515,0xad962aaa,0x2f5a2993,0x2e99a765,
0x2ff42ddc,0x2e1f2ed0,0x2e1f2fe6,0xa875afff,0xa8142c87,0xaffca9f1,0xadfe1648,0x2e5e2e99,0xaf5aaf30,0x2eb5a814,0xac5dafed,0xb000a934,0x2c32a8d5,0xa9932e3f,0x2f462875,0x2e7ca8d5,
0x2e991fd9,0x30002814,0x2f6e2ee9,0xac87af91,0x29932fa0,0xaed02875,0xacb02875,0x2f462d27,0xaff4ac32,0x2b5eaddc,0xad27afff,0xaff4a515,0x244ead96,0x1fd92fd4,0x2f3026a1,0x2e5ea9f1,
0x2814ad27,0x2dfeabb7,0x2ffc2d00,0xae5eae1f,0x2e992f80,0xaa4e2e7c,0xaa4e2c32,0x2fd42aaa,0xae7c1648,0x9cb6afdd,0xaddcafd4,0xafc91648,0xa875af91,0x2b5e2fbc,0x2f1a244e,0x2e3fab05,
0xab05aff4,0x244eafa0,0x2fbc28d5,0xaf91abb7,0x30002c32,0x26a12fff,0xa5db2ddc,0x30002515,0xaaaa2c5d,0xac32af6e,0xae7caf6e,0xaf8025db,0xad27afed,0x2e3f2dfe,0x2f021fd9,0x2e1fac07,
0xaf5aae5e,0xac5daf30,0x2eb59fd9,0xb000a44e,0x2e7ca30e,0x2ddc2e1f,0x1cb62f1a,0x2fc9a30e,0x217e2f46,0xaf02acb0,0xaf02aed0,0xaf1a2993,0xaf30ae99,0x2fbc29f1,0x2ee99648,0x2dfeac87,
0xafa0a515,0xafafa993,0x2d00aaaa,0xafa02765,0x2934ad96,0x2fed26a1,0x28142fd4,0x2f30a9f1,0x2c872fed,0xb0009fd9,0xaf6eadfe,0xae992c07,0xafffabb7,0x2fe6a17e,0x2ed0a17e,0x2ddcad00,
0xac322c87,0xaf462a4e,0x2993adba,0xae7c2c87,0xa875afed,0x2f1aab05,0x2b5e2ffc,0x2e3facd8,0x2f302e1f,0xaee92bb7,0xafbcad00,0xadfe2d27,0xaf6e9cb6,0x2eb5ac32,0x2eb5a515,0x2dbaad72,
0xaaaa2f5a,0xaed02e99,0xacb02e99,0x2f80ad96,0x2b5eaf30,0x2fafa44e,0x2d00ae5e,0xaf1a9fd9,0xac072f02,0xab05ad27,0xad4d2e1f,0x28142e3f,0x2c5daed0,0xa9f12fff,0x2d96addc,0x2c5dafe6,
0x28752f80,0xa8d52fe6,0xa8d52fc9,0x2e3faf46,0xa44eafd4,0x2f91adba,0x2b05af6e,0xafbc26a1,0x96482ffc,0xae99a44e,0xac872ee9,0x29f12d4d,0x2515aff8,0x1cb62f02,0x2d72ae3f,0x2c32aff8,
0x2eb52b05,0x2a4e2cd8,0x16482fed,0x2c5daffc,0xad72ad27,0x2cb0aff4,0x2765aff4,0xafff2b5e,0x2bb72e7c,0xaff82aaa,0xab5e2f80,0x2bb72c32,0xa814af6e,0x2b052c87,0x2d4dae99,0x2c07b000,
0x2feda8d5,0x2f30a30e,0x29342f02,0x2814afa0,0xafd49cb6,0x1648aed0,0x1648afe6,0xafdd2d72,0x2ed029f1,0xaf462eb5,0xa9932fdd,0x2cb029f1,0xad00ad4d,0x2e1f244e,0x2d27aee9,0x2bb7affc,
0x2d4daf02,0x2fbcae1f,0x2cd82d27,0x9fd9ae3f,0xaf5a2cb0,0xac87a993,0xa6a1af46,0xaf5a2ed0,0x2fffa5db,0xacb03000,0xa7653000,0x2d7226a1,0xaf1aa814,0x2fafa934,0x2d00af30,0x2b5eafed,
0x1648afbc,0x2c87affc,0x2e992934,0xa9f1ac07,0xac322faf,0xaf8028d5,0xaaaaae1f,0xae7c2faf,0x2f1aad72,0xa30e2ed0,0xa30e2fe6,0x2e1f1cb6,0xaffc26a1,0x2fedadba,0x2cd8af6e,0x2b05afd4,
0xad27ac32,0xa30ead72,0x2faf9cb6,0xad27a515,0x1fd92f6e,0xafbc2e99,0xacd8ac87,0xad4d3000,0x2c5dafbc,0x2a4e2b05,0x16482f91,0x2eb5a44e,0xaf802d00,0x2ed0afa0,0x2cb0afa0,0x2aaaafaf,
0xafe626a1,0xaddc1648,0x2fffaa4e,0xaed026a1,0x2d002c07,0xad272ffc,0xae1fa934,0xabb72fbc,0x1fd9afa0,0x2e5ea30e,0x244e2f02,0x2f30a8d5,0xadba2f46,0x2c87afe6,0x2c87afc9,0x2a4eaf80,
0xafff2d96,0xae7c2c5d,0xafc92c5d,0x2d72a9f1,0xa17e2dfe,0xaff42fbc,0xa8752ee9,0x2ff8af30,0x2fedad00,0xad4d2f1a,0x2f91ab5e,0x2e5eafaf,0x25dbae7c,0x16482993,0x29f1af46,0x25dbac32,
0xae3f2fff,0xaff82fc9,0xaff82e7c,0x2f02ad72,0x2c0725db,0xadfe2f5a,0x9fd92d96,0x2fedafdd,0x2f6eaf91,0xa6a12c07,0x2fd4acd8,0x2dbaaf30,0xa765ab5e,0x2aaaa30e,0x2993af02,0x2515ab5e,
0xa5db2dfe,0xad962ee9,0xaf5a2fbc,0x2fddaf30,0x2f46ab5e,0xa7652bb7,0x25152bb7,0x2f80aff8,0x2d00afc9,0x28d59cb6,0x2ff8addc,0x2d00ae7c,0xacd89648,0x2dfeac5d,0x2934aeb5,0x244eaa4e,
0x2c07217e,0x9fd92875,0xadfe2ff4,0x2fedaff8,0x2fddaf46,0x29f1a515,0x29f12765,0x2eb5af80,0x2515ad96,0x2ddcac87,0x2fffaeb5,0x2c32ad96,0xaf022b05,0x2fa0aee9,0x28d5ae5e,0x230ea934,
0x2f91ad00,0x2cd8ab5e,0xac072f1a,0x2f30afaf,0x2d96afc9,0x2eb5addc,0x2c879cb6,0x2d96ae7c,0xa993a6a1,0x2fc9af5a,0x2fe6af5a,0x2aaaac87,0xaff82e5e,0x2ff4affc,0x2875adfe,0x217ea814,
0x2f6eafed,0x2fd4af91,0xa6a12d4d,0x2dbaae5e,0x2515ad00,0x2fffaff8,0x2ddca8d5,0x2c32ad00,0xae1f2993,0x2fafafe6,0x2fafafc9,0x28d5aaaa,0xaf912fdd,0x2ee9af5a,0x2814ad96,0x1fd9a5db,
0x2b5eae7c,0x2f02af46,0x230e2993,0x2b5eac32,0xab059648,0x2e5eaeb5,0x2ee9ac5d,0x2934aa4e,0xafdd2e5e,0x2d96adfe,0x2f5aaffc,0x25dba814,0xaddc2faf,0x2cb0ad27,0x2765ad27,0x1cb6a30e,
0xa765a5db,0x2993a9f1,0x2aaa9648,0x2515a5db,0xaf022cd8,0x28d5a934,0x2fa0adfe,0x230ea44e,0xaf912ff8,0x2814a875,0x2ee9aff4,0x1fd9a17e,0xaa4e2ddc,0x26a1a765,0x26a1acb0,0x16489cb6,
0x2d722d96,0x25152c5d,0x2c322c5d,0x1cb6a9f1,0x2d272d4d,0xad00a814,0x2bb72c07,0x2e1f2b05,0x2cd82d00,0xaffcaf1a,0x2b052b5e,0x2fed2faf,0x2c872cb0,0xadbaaf80,0x2a4e2aaa,0x2c872ed0,
0x2e3f2ddc,0x2ff82ed0,0x2ff82fe6,0xaf02afff,0x2ee92e99,0x2d4d2f6e,0x2ffc3000,0xa44eac87,0x2f6e2f30,0xa6a12814,0x2fd42fed,0x2dba2934,0x2fc92fa0,0xaf46ad00,0x2f802faf,0x2fe62fa0,
0xac87ad4d,0x9648ac07,0x29f12814,0xae99ab05,0xa993ab5e,0x2ed02bb7,0x2cb02bb7,0xaf46aff8,0xa30ea765,0x2f1a2fff,0x2e1f2d72,0xa30eacb0,0x244e1648,0x1fd92c5d,0x2f302eb5,0x2e5e2a4e,
0xaee9ae1f,0xaffcaf02,0xad4dae3f,0x244e2d27,0xafddaf80,0xa9f1ae7c,0xa9f1ac32,0xaeb5aaaa,0xafe6b000,0x2d7225db,0x9cb6a6a1,0xaed0b000,0xaf02af91,0x2fa02fbc,0x28d5244e,0x230eab05,
0x2b052d00,0xa44e2b5e,0xafbcaf1a,0x2f912faf,0x16482765,0xafd4ad72,0xafddafff,0x16482cb0,0xaaaaa6a1,0xac32af5a,0xae7caf5a,0xaf80ac87,0xae1facd8,0x2d001fd9,0xabb7ad4d,0xad27afbc,
0x2f6e2e5e,0x2fd42f30,0xa6a11fd9,0x2dba244e,0x2fe62ff4,0x1cb62d27,0xad72ab5e,0x2ed02ff4,0x2e1f2f46,0xafafacb0,0xafafaed0,0xa8d52993,0x29342c87,0xac07af6e,0xafbcb000,0xaffcae99,
0xa8d5acb0,0x2875aaaa,0x2e3f2f80,0xa8d5aed0,0x29341648,0x2fed2eb5,0x28142c5d,0x2f302a4e,0x2e992cd8,0x16482d4d,0xa9f19fd9,0x2c872fbc,0x2fff2faf,0xafe6ad27,0xaed0ad27,0xaddca30e,
0xafc9ae99,0xaf80af5a,0x2f462d96,0xafe6ae99,0xaf02afed,0x28d5ab05,0x2fa02ffc,0x230eacd8,0xa934ad27,0x2fbc2f02,0x2c072e3f,0x2ffc2e1f,0x2a4e1cb6,0xa6a12c32,0xa6a12515,0x96482d72,
0xaaaa29f1,0xaed025db,0xacb025db,0x2f801648,0xaf1aaf91,0x2875ae5e,0xae3fafed,0xab5e2d4d,0x2c07a875,0x2b052ff8,0x2d4da17e,0xa814aff4,0x2eb52fc9,0xaf6ead72,0x2dba2fff,0x2eb52e7c,
0x2f022f80,0x2b5e2fe6,0x2b5e2fc9,0x230eaf46,0xacd826a1,0xaf30ad96,0xaf91a9f1,0x2c072fd4,0xad96affc,0x2fdd244e,0xa5dbaee9,0xaf5aad4d,0x2e7c217e,0xad722bb7,0x2fff2d00,0x2fc9217e,
0x2c5da934,0x2f5aa44e,0x30002cd8,0xaeb5adfe,0x2d722ff8,0xacb02d00,0xa7652d00,0x2fff28d5,0xaf02a515,0x217eaf80,0xaf1aaf46,0xaf022765,0xa814af5a,0x2b052fdd,0x2d4da5db,0x2c07ad96,
0xae5eafa0,0xa934aff4,0x2b05abb7,0xaee928d5,0x2eb51cb6,0x2d962ed0,0x2d962fe6,0x2c87ad72,0x27652f6e,0xaf80ac5d,0xaf46a5db,0xa5152f6e,0xaff4ad4d,0x2ff8244e,0xa17eaee9,0xa875affc,
0xad4d2875,0xafbc217e,0xacd8aff8,0x1fd92ff4,0xaa4eafe6,0x2e99aaaa,0x2fd42993,0xaa4eafc9,0x2fff2c87,0xacb02d96,0xa7652d96,0x2d722eb5,0xab5e2c07,0x2875af30,0xae3faf91,0xaf1aacd8,
0x2d962fbc,0x25db2ffc,0xafdda934,0x2f5a2c07,0xafc9a875,0xaaaaafa0,0x2993ad27,0xafe6a875,0x28d5ad72,0x2d002ed0,0x2d002fe6,0x2ff81cb6,0x2d4d2fd4,0xae5ead96,0xafeda9f1,0xaf9126a1,
0x2e1fa765,0x2ff49cb6,0xa8752ddc,0x2e1facb0,0x1fd92f5a,0xafbc25db,0xacd8afdd,0xad4d2d96,0xaeb5aee9,0x2f5aa934,0x30002b05,0x2c5dae5e,0x2f80230e,0xaed02b5e,0xacb02b5e,0xaaaa2f02,
0xacb0afd4,0x9cb6b000,0x2ddc2f5a,0xa765afd4,0x2ff42c07,0x217e2ffc,0xaff8a934,0x28752fbc,0xadfe28d5,0xa44eaff4,0x2cd8abb7,0xa934afa0,0x1648af46,0x25db2fe6,0x25db2fc9,0x29f12f80,
0xafff9648,0xae7ca6a1,0xafc9a6a1,0x2d722a4e,0x2ff81fd9,0x230e2ee9,0x2faf2814,0x217eaf91,0xafeda30e,0x2d4dafa0,0xaf91a8d5,0xae5e2f02,0x2fdd2515,0xb0002aaa,0x2f6e2993,0x2fdda765,
0xa30e2fff,0xad272fc9,0xad272e7c,0x2fafad72,0x2814afdd,0x2ffcaa4e,0x2dfeadba,0xae5ea5db,0xaa4e2f91,0xac5dac07,0xaeb52cd8,0x96482f30,0x2c32af1a,0xa9932ff4,0x2f46abb7,0x2e7caf1a,
0x2fdd1fd9,0x2dba2814,0x2a4e2ee9,0x25dbaf91,0xaf46a8d5,0x2765afaf,0xa515afaf,0xaf802e1f,0x2e3f2c32,0xafa02ddc,0xa17e2fff,0x2e3f2515,0xacd8adba,0x2dfe26a1,0x2934afd4,0x244eaf6e,
0x2814aff8,0x2dfeafaf,0x2ffca30e,0xae5ea17e,0xac872f46,0xaf5a2515,0xaf5aa765,0xa6a12f80,0x2e7cadba,0x1cb62e99,0x2ddc2c5d,0x2fc9adba,0xafaf2b05,0x2f1aaee9,0xab5eae5e,0xad00a934,
0xaf91a30e,0xacd8a8d5,0x2c07afa0,0xaf302f02,0x2dba2c32,0xac5d2fff,0xae992ddc,0x2dba2515,0xa993aeb5,0x2fc9a9f1,0x2fe6a9f1,0x2aaaafdd,0xa17e2fed,0xa30eadfe,0xafaf9fd9,0xaff82c07,
0xaa4e2fed,0xaeb52f91,0xac5dad4d,0x96482e5e,0x2e7cae3f,0x2ddc217e,0x1cb62fa0,0x2fc9ae3f,0xaff82993,0x2bb7afe6,0x2bb7afc9,0xab5eaaaa,0x2f3025db,0xafbc2a4e,0xaee92dba,0xadfe2fdd,
0x2f1a2515,0x2bb72993,0xaff42aaa,0x2f1aa765,0xab05adba,0x2e5eafd4,0x2ee926a1,0x2934af6e,0xa5db2fed,0xadba9fd9,0xaa4eadfe,0xafdd2c07,0x2ddcaf02,0xacb02ff8,0xa7652ff8,0x9cb62e3f,
0x2c32afdd,0x2f46af6e,0xa9933000,0x2e7cafdd,0xafaf2cd8,0xab5ea934,0x2f1aadfe,0xad00a44e,0x2f30217e,0xaee92faf,0xafbc230e,0xadfe2ff8,0xa9f1addc,0x2c5d2765,0x2c5d2cb0,0x2d961cb6,
0xa993aa4e,0x2765ac87,0xa515ac87,0xaaaa2dba,0xafa02f30,0xabb7244e,0xaff42e5e,0x28d51fd9,0x28142bb7,0xaf912e1f,0x1fd92d27,0x2ee9ad00,0x2fd4aed0,0xaf5a2fff,0x3000addc,0x2fd4afe6,
0xafaf2f46,0xafa02e7c,0xafa02c32,0x2d00a993,0x244e2c5d,0xaf913000,0xab052f5a,0x2fbcaeb5,0x3000adfe,0xac872e5e,0x2e99a814,0x2f6eaffc,0x2515ae1f,0x1cb62875,0x2d72aff4,0x2c32ae1f,
0x26a12b05,0xa9f12cd8,0xad962fed,0x2fd4affc,0x2fffae1f,0x2515230e,0x2c32230e,0x2ddcaf1a,0x2875ae7c,0x2d27aaaa,0x2fa0af80,0x2875ac32,0xaee929f1,0x2f91ae99,0x9fd9ac87,0xa8149648,
0x2fedaf1a,0x2f30ae3f,0x29342875,0x2814ab5e,0x26a1addc,0x3000afc9,0x3000ae7c,0xa5db9cb6,0xaed02a4e,0x2f46afd4,0x2993ae99,0xacb02a4e,0xae3f2ffc,0x2d27ae5e,0xae1f2814,0xaf022dfe,
0x9fd9abb7,0x2c07ad27,0x2fedae1f,0xadfe2d00,0xaf6e2cb0,0x25dba993,0x2c5daf46,0xaf6e2ed0,0xaddc2fdd,0xa5159648,0xac329648,0xafff2fd4,0x28d52814,0xabb72934,0xaff42f30,0xafa02fed,
0xb0002ee9,0xae992dfe,0x2c87af30,0xaf6e2fbc,0xac322f02,0xaf802f1a,0xaaaaa17e,0xae7c2f02,0x2b5e1cb6,0xaff42fc9,0xaff42e7c,0xad272ddc,0x2ffcaeb5,0xafed3000,0xacd82f5a,0xab052c5d,
0xa17e2c32,0xad002d72,0xabb71cb6,0xa17e2515,0x2dfea9f1,0xac072c87,0xafed2e99,0x1fd91648,0x2fd4afbc,0xa9f12b05,0xad962f91,0x26a1a44e,0x2aaaae3f,0xa76528d5,0x251528d5,0x2993a875,
0x2fe6aeb5,0x2ddcadba,0xafff2f6e,0x2ed0aeb5,0x2e3fafbc,0x2e1fadfe,0xad272f30,0x2f02aee9,0x1fd9ab5e,0x2e5eae3f,0x244e2875,0x2f30af1a,0xad962993,0x2e99ae7c,0x2e99ac32,0x2f5aaf46,
0x299329f1,0xa76525db,0x251525db,0x2aaa1648,0x28d52934,0xaf02acd8,0x230e244e,0x2fa02dfe,0x28142875,0xaf91aff8,0x1fd9217e,0x2ee92ff4,0x26a12765,0xaa4eaddc,0x16481cb6,0x26a12cb0,
0x2f022f46,0x2b5e2e7c,0x2b5e2c32,0x230ea993,0x2e5e2eb5,0xab051648,0x29342a4e,0x2ee92c5d,0x2d962dfe,0xafddae5e,0x25db2814,0x2f5a2ffc,0x2cb02d27,0xaddcafaf,0x1cb6230e,0x27652d27,
0x2fd42f91,0x2f6e2fed,0x2dba2e5e,0xa6a1ad4d,0x2fff2ff8,0x25152d00,0x2c322d00,0x2ddc28d5,0x2faf2fe6,0xae1fa993,0x28d52aaa,0x2faf2fc9,0x2ee92f5a,0xaf91afdd,0x1fd925db,0x28142d96,
0x2cd82b5e,0x2f912d00,0x2f302faf,0xac07af1a,0x2eb52ddc,0x2d962fc9,0x2d962e7c,0x2c871cb6,0x2fc92f5a,0xa99326a1,0x2aaa2c87,0x2fe62f5a,0x2ff42ffc,0xaff8ae5e,0x217e2814,0x28752dfe,
0x9fd9a875,0x2c07a17e,0x2fed2ff8,0xadfeaff4,0x29f12515,0x2fdd2f46,0x2eb52f80,0x29f1a765,0x2ddc2c87,0x25152d96,0x2c322d96,0x2fff2eb5,0x2fa02ee9,0xaf02ab05,0x230e2934,0x28d52e5e,
0xad96aee9,0xa5dbadfe,0x2fdd2f30,0xaf5aafbc,0xa765abb7,0x2f462b5e,0x2f802ff8,0x2515abb7,0x28d51cb6,0x2d002fc9,0x2d002e7c,0x2ff82ddc,0x2dfe2c5d,0xacd81648,0x244e2a4e,0x29342eb5,
0xaff8afc9,0xae3fafff,0x2f022d72,0xaff8ae7c,0xadfeaf5a,0x2c07a5db,0x2fed2fdd,0x9fd9ad96,0xa6a1ac07,0x2f6e2f91,0x2dba2f30,0x2fd42cd8,0x2aaa230e,0xa7652b5e,0x25152b5e,0x29932f02,
0xae7cac5d,0xafffad96,0x2d7229f1,0xafc9ac5d,0xaff4afbc,0xa17eadfe,0x2ff82f30,0xa875aee9,0xad4daf1a,0x2fed2d00,0x2e5e2faf,0x2f912b5e,0x1648a993,0x25db2e7c,0x25db2c32,0x29f12f46,
0xaddc9648,0xafe6a6a1,0xaed0a6a1,0x2fff2a4e,0xad27affc,0x2d00ac07,0xabb7afbc,0xae1f2934,0x2e5e230e,0x1fd92fa0,0x2f3028d5,0x244eaf02,0x2c872fe6,0xadbaaf46,0x2a4e2f80,0x2c872fc9,
0xa30e2d72,0xad272c32,0xad272515,0x2faf1cb6,0xafbcae99,0x1fd9af6e,0xad4db000,0xacd82c87,0x2a4eab05,0x2c5d2fbc,0x2eb5244e,0x1648af91,0x2ed02fa0,0xaf80ad00,0x2aaa2faf,0x2cb02fa0,
0x2c872ffc,0x16482fbc,0xa9f12c07,0x2e99a934,0xaf80a8d5,0xac32afaf,0xae7cafaf,0xaaaa2e1f,0xa30eaed0,0x2f1a2d72,0x2e1f9cb6,0xa30eafe6,0x2fed2dba,0xaffca6a1,0x2b052fd4,0x2cd82f6e,
0x2fbc2e1f,0x2d4d2f02,0x9fd92e3f,0x2cd8ad27,0xac872993,0xaf5aacb0,0xaf5aaed0,0xa6a12f46,0xacb0b000,0x2fff25db,0x2d72a6a1,0xa765b000,0x2faf2934,0xaf1a2814,0x2b5e2fed,0x2d002f30,
0x2f30230e,0x2fed28d5,0x28142fa0,0x2934af02,0x16482ed0,0xafd41cb6,0xafddad72,0x16482fe6,0xaf46aeb5,0x2ed0a9f1,0x2cb0a9f1,0xa993afdd,0x2e1fa44e,0xad002d4d,0x2bb72ffc,0x2d272ee9,
0x2a4eacd8,0x2eb5ab05,0x2c5d2ffc,0x1648afed,0x2cb02ff4,0xad722d27,0xafffab5e,0x27652ff4,0xaff8aaaa,0x2bb7ae7c,0x2bb7ac32,0xab5eaf80,0x2b05ac87,0xa8142f6e,0x2c073000,0x2d4d2e99,
0xa8d5afe6,0x2875af80,0x2e3f2f46,0xa8d5afc9,0x2f912dba,0xa44e2fd4,0xafbca6a1,0x2b052f6e,0xae99244e,0x9648affc,0x29f1ad4d,0xac87aee9,0x1cb6af02,0x25152ff8,0x2c322ff8,0x2d722e3f,
0xaed0ae99,0xaaaaaf5a,0x2f802d96,0xacb0ae99,0x2faf244e,0x2b5e2f30,0xaf1a1fd9,0x2d002e5e,0xab052d27,0xac07af02,0x2814ae3f,0xad4dae1f,0xa9f1afff,0x2c5d2ed0,0x2c5d2fe6,0x2d962ddc,
0xaf46aa4e,0xac32ac87,0xae7cac87,0x29932dba,0x2f1a2b05,0xa8752fed,0x2e3f2cd8,0x2b5eaffc,0xaee9abb7,0x2f30ae1f,0xadfead27,0xafbc2d00,0x2eb52c32,0xaf6e1cb6,0x2dba2d72,0x2eb52515,
0xafaf2993,0xafa02515,0xafa0a765,0x2d002aaa,0x2feda6a1,0x29342d96,0x2f3029f1,0x2814afd4,0xb0001fd9,0x2c87afed,0xae99ac07,0xaf6e2dfe,0x2fe6217e,0xafff2bb7,0x2ddc2d00,0x2ed0217e,
0xac5d2f30,0xaf5a2e5e,0xb000244e,0x2eb51fd9,0x2ddcae1f,0x2e7c230e,0x2fc9230e,0x1cb6af1a,0xaf022cb0,0x217eaf46,0xaf1aa993,0xaf022ed0,0x2fbca9f1,0xaf302e99,0x2dfe2c87,0x2ee91648,
0x244e2fa0,0xab052ff4,0xaf912bb7,0x2fbca8d5,0x26a1afff,0x3000ac32,0x3000a515,0xa5dbaddc,0xac322f6e,0xaaaaac5d,0xaf80a5db,0xae7c2f6e,0x2e3fadfe,0xad272fed,0x2e1f2c07,0x2f029fd9,
0x2dfe2bb7,0x28142d27,0xae5e2e1f,0x2ffcad00,0xaa4eae7c,0x2e99af80,0x2fd4aaaa,0xaa4eac32,0x9cb62fdd,0xae7c9648,0xafc99648,0xaddc2fd4,0x2b5eafbc,0xa8752f91,0x2e3f2b05,0x2f1aa44e,
0x3000a814,0x2e999fd9,0xac872f91,0x2f6eaee9,0xaed0a875,0x2993afa0,0x2f46ad27,0xacb0a875,0x2b5e2ddc,0xaff42c32,0xaff42515,0xad272fff,0x1fd9afd4,0x244e2d96,0x2e5e29f1,0x2f30a6a1,
0x2e1faed0,0x2ff4addc,0xa8752fff,0x2e1fafe6,0xaffc29f1,0xa814ac87,0x2e5eae99,0xadfe9648,0x2eb52814,0xaf5a2f30,0xb0002934,0xac5d2fed,0xa993ae3f,0x2c3228d5,0x2e7c28d5,0x2f46a875,
0x2515afd4,0x2d72b000,0x1cb62f5a,0x2c32afd4,0xae3f2ee9,0xae1f1fd9,0x2d27af91,0xaf022814,0x2ffca8d5,0xacd82ff4,0xafed2bb7,0xab052fa0,0xad96aaaa,0x2e99a515,0x2e992765,0x2f5aa993,
0x1cb6adba,0x2cb0aeb5,0x2765aeb5,0xaddc2f6e,0xaff82d4d,0xa30ea814,0xafaf2c07,0xa17e2b05,0xa44e2e3f,0xadfe2b5e,0xa9342f1a,0x2cd8a875,0x2fddacb0,0xb0002f80,0x2f6eaaaa,0x2fddaed0,
0xad009cb6,0xa17ea765,0xa17eacb0,0xabb72ddc,0xaee92fdd,0xad4d2a4e,0xaffc2dba,0x244e25db,0x29f12934,0xafd42ee9,0xa6a12e5e,0x2d96ab05,0x2fc9af1a,0xaf462ff4,0x2f80abb7,0x2fe6af1a,
0xafdd2d4d,0xadba2c07,0xaa4ea814,0xa5db2b05,0xaaaa2f1a,0xafc92f02,0xafe62f02,0x2993a17e,0x2e3fa765,0xafa02fff,0xa17e2d72,0x2e3facb0,0x2e5eb000,0xad4d2eb5,0x2f91ac5d,0x2fedaf5a,
0xaee92ff8,0xaffc2faf,0xad4d230e,0x244e217e,0x25db2aaa,0xaf6e2fe6,0xaf6e2fc9,0x2c5da993,0x2fe6adba,0xad722e99,0x1cb62c5d,0x2ed0adba,0x2bb7af30,0xa8d52c07,0x2fa0acd8,0x2ff4af91,
0xa9342e3f,0xae5e2f1a,0xaee92b5e,0x2b05a875,0x2dbaa765,0xac5d2d72,0xae992fff,0x2dbaacb0,0x2f80afd4,0xa7652a4e,0x25152a4e,0x2f46ae99,0x217eacd8,0x230e1fd9,0x2fafad4d,0x2ff8afbc,
0x29f1244e,0xa6a12934,0xafd42dfe,0x2d96acd8,0x2fe6ae3f,0x1cb6217e,0xad722fa0,0x2ed0ae3f,0x2d27af80,0x2875a515,0x28752765,0x2fa0af46,0xa934a5db,0x2c07aa4e,0x2fbcadba,0x2ffcafdd,
0x2f1aacb0,0x2bb7aaaa,0xaff42f80,0x2f1aaed0,0x2f30b000,0x2cd8ac5d,0xac072eb5,0x2f91af5a,0x25dbacd8,0x2dbaad4d,0x2a4e1fd9,0x2fddafbc,0xad722875,0x2e7cae1f,0x2fc9ae1f,0x2fffaff4,
0x2fc9afdd,0x2f80af6e,0xaf463000,0x2fe6afdd,0x2bb7ae5e,0x2fa0af91,0xa8d52d4d,0x2ff4afed,0xa934a17e,0x2fbcafaf,0x2c07a30e,0x2ffcaff8,0xaf5a2d72,0x2fd4afc9,0x2fd4ae7c,0x3000afff,
0x3c003c00,0x3bff3c00,0x3c003c00,0x3bfa3bfd,0x3c003c00,0x3bef3bf5,0x3c003c00,0x3bde3be7,0x3c003c00,0x3bc83bd4,0x3c003c00,0x3bac3bbb,0x3c003c00,0x3b8b3b9d,0x3bff3c00,0x3b653b79,
0x3c003c00,0x3bff3c00,0x3c003c00,0x3bf83bfd,0x3bff3c00,0x3bea3bf2,0x3bff3bff,0x3bd63be1,0x3bfe3bff,0x3bba3bc9,0x3bfd3bfe,0x3b983baa,0x3bfc3bfd,0x3b6f3b84,0x3bfb3bfc,0x3b3f3b58,
0x3c003c00,0x3bff3c00,0x3bff3c00,0x3bf63bfc,0x3bfe3bff,0x3be53bef,0x3bfd3bfe,0x3bcc3bda,0x3bfb3bfc,0x3bab3bbc,0x3bf93bfa,0x3b813b97,0x3bf63bf7,0x3b4f3b69,0x3bf23bf4,0x3b163b33,
0x3c003c00,0x3bff3c00,0x3bff3c00,0x3bf53bfb,0x3bfd3bfe,0x3be03bec,0x3bfa3bfc,0x3bc23bd2,0x3bf63bf8,0x3b9a3baf,0x3bf23bf4,0x3b683b82,0x3bec3bef,0x3b2c3b4b,0x3be53be9,0x3ae83b0b,
0x3c003c00,0x3bfe3c00,0x3bfe3bff,0x3bf23bfa,0x3bfb3bfd,0x3bda3be8,0x3bf63bf9,0x3bb73bca,0x3bf03bf4,0x3b873ba0,0x3be83bed,0x3b4c3b6b,0x3bdf3be4,0x3b073b2b,0x3bd43bda,0x3ab63ae0,
0x3c003c00,0x3bfe3c00,0x3bfd3bff,0x3bf03bf9,0x3bf93bfb,0x3bd43be4,0x3bf23bf6,0x3bab3bc1,0x3be83bed,0x3b733b91,0x3bdd3be3,0x3b2f3b53,0x3bcf3bd6,0x3ade3b08,0x3bbf3bc7,0x3a813ab1,
0x3c003c00,0x3bfe3c00,0x3bfc3bfe,0x3bee3bf8,0x3bf63bf9,0x3bce3be0,0x3bec3bf1,0x3b9e3bb7,0x3bdf3be6,0x3b5e3b80,0x3bcf3bd7,0x3b103b39,0x3bbc3bc6,0x3ab33ae3,0x3ba53bb1,0x3a493a7f,
0x3bff3c00,0x3bfe3c00,0x3bfb3bfe,0x3beb3bf7,0x3bf23bf7,0x3bc63bdb,0x3be53bed,0x3b903bad,0x3bd43bdd,0x3b473b6e,0x3bbf3bca,0x3aee3b1d,0x3ba53bb2,0x3a853abc,0x3b873b97,0x3a0d3a4b,
0x3bfd3c00,0x3bfa3c00,0x3be83bf6,0x3bcc3be9,0x3bbf3bd6,0x3b713ba4,0x3b813ba2,0x3aeb3b33,0x3b2f3b5a,0x3a3d3a99,0x3acb3aff,0x396b39d8,0x3a543a92,0x387a38f6,0x39cd3a13,0x36dd37ee,
0x3bfd3c00,0x3bfa3c00,0x3be53bf4,0x3bc83be7,0x3bb73bd1,0x3b653b9d,0x3b713b97,0x3ad53b22,0x3b163b46,0x3a193a7c,0x3aa53ae0,0x393739ad,0x3a213a65,0x383538ba,0x398b39d8,0x36313753,
0x3bfd3c00,0x3bf93c00,0x3be23bf3,0x3bc33be5,0x3bae3bcb,0x3b593b95,0x3b603b8a,0x3abd3b11,0x3afb3b30,0x39f43a5e,0x3a7e3abf,0x39023980,0x39eb3a37,0x37dd387c,0x3946399b,0x358136b5,
0x3bfc3c00,0x3bf93c00,0x3bdf3bf1,0x3bbf3be3,0x3ba53bc6,0x3b4c3b8c,0x3b4f3b7d,0x3aa53aff,0x3ade3b1a,0x39cd3a3f,0x3a543a9c,0x38cc3951,0x39b33a07,0x374e383d,0x38fd395b,0x34cf3614,
0x3bfc3c00,0x3bf83c00,0x3bdc3bf0,0x3bba3be1,0x3b9c3bc0,0x3b3f3b84,0x3b3d3b70,0x3a8c3aed,0x3ac13b02,0x39a63a1f,0x3a293a78,0x38943922,0x397939d4,0x36bb37f9,0x38b23918,0x341a3570,
0x3bfc3c00,0x3bf83c00,0x3bd83bee,0x3bb53bdf,0x3b923bb9,0x3b323b7b,0x3b2a3b62,0x3a733ad9,0x3aa23ae9,0x397d39fe,0x39fc3a52,0x385a38f1,0x393c399f,0x36253775,0x386538d3,0x32c634c9,
0x3bfb3c00,0x3bf73c00,0x3bd43bed,0x3bb03bdc,0x3b873bb2,0x3b243b72,0x3b163b53,0x3a583ac6,0x3a813ad0,0x395439dc,0x39cd3a2b,0x382038bf,0x38fd3969,0x358d36ee,0x3815388c,0x31533420,
0x3bfb3c00,0x3bf63c00,0x3bd03beb,0x3bab3bda,0x3b7c3bab,0x3b163b69,0x3b013b43,0x3a3d3ab1,0x3a603ab5,0x392939ba,0x399d3a02,0x37c8388c,0x38bc3930,0x34f33665,0x37853842,0x2fbd32ea,
0x3bf63c00,0x3bf03c00,0x3ba53bd7,0x3b733bc1,0x3b073b5f,0x3a813b08,0x3a213a9c,0x392939e1,0x38fd3996,0x36ff385d,0x374e3858,0x327c3529,0x345735da,0xa9b12d1a,0x2cce3191,0xb49fb160,
0x3bf53c00,0x3bef3c00,0x3b9f3bd5,0x3b6c3bbe,0x3af73b55,0x3a6f3afc,0x3a043a87,0x390739c7,0x38d13972,0x36993832,0x36d23822,0x316c34b1,0x3371354c,0xad65297f,0x27763036,0xb552b2b9,
0x3bf53c00,0x3bef3c00,0x3b9a3bd2,0x3b653bbb,0x3ae83b4b,0x3a5c3af0,0x39e73a71,0x38e539ad,0x38a3394d,0x36313807,0x365437d8,0x305b3438,0x323234bd,0xafef1e48,0xa4522db0,0xb602b408,
0x3bf43c00,0x3bee3c00,0x3b943bd0,0x3b5e3bb7,0x3ad83b41,0x3a493ae3,0x39c93a5a,0x38c13992,0x38743927,0x35c837b7,0x35d4376a,0x2e91337d,0x30f0342c,0xb13ba7da,0xac0629e3,0xb6afb4b1,
0x3bf33c00,0x3bed3c00,0x3b8e3bcd,0x3b573bb4,0x3ac73b36,0x3a353ad6,0x39aa3a43,0x389e3976,0x38453900,0x355e375e,0x355236f9,0x2c6a3288,0x2f593334,0xb27cac51,0xaef51a48,0xb759b558,
0x3bf23c00,0x3bec3c00,0x3b873bca,0x3b4f3bb1,0x3ab63b2b,0x3a213ac9,0x398b3a2b,0x387a395b,0x381538d8,0x34f33705,0x34cf3687,0x28843191,0x2cce320d,0xb3baaeaa,0xb0f0a91b,0xb7feb5fd,
0x3bf23c00,0x3beb3c00,0x3b813bc7,0x3b473bad,0x3aa53b20,0x3a0d3abc,0x396b3a13,0x3855393e,0x37c838b0,0x348736aa,0x344b3614,0x16483099,0x288430e4,0xb47bb080,0xb263ad4c,0xb850b69e,
0x3bf13c00,0x3bea3c00,0x3b7a3bc4,0x3b3f3baa,0x3a933b14,0x39f83aae,0x394a39fa,0x38303922,0x37643887,0x341a364e,0x3389359f,0xa81f2f40,0x9cb62f72,0xb517b1aa,0xb3d3b004,0xb89eb73d,
0x3be93c00,0x3be13c00,0x3b373ba6,0x3af13b86,0x39e33aa0,0x392e3a27,0x380a3905,0x3599380d,0x335935f1,0x217f31db,0xac382d4c,0xb546b12e,0xb5b1b2d2,0xb90cb7cd,0xb8eab7d8,0xbadbba0b,
0x3be83c00,0x3be03c00,0x3b2f3ba2,0x3ae83b82,0x39cd3a92,0x39163a17,0x37c838e7,0x354637d8,0x327c3593,0xa4523115,0xae5f2aac,0xb5c8b226,0xb648b3f7,0xb94ab828,0xb933b838,0xbb0aba43,
0x3be73c00,0x3bdf3c00,0x3b273b9e,0x3ade3b7d,0x39b83a83,0x38fd3a07,0x377a38c9,0x34f33796,0x319e3534,0xa9b1304e,0xb042257f,0xb648b31b,0xb6ddb48d,0xb986b867,0xb979b881,0xbb35ba78,
0x3be63c00,0x3bde3c00,0x3b1e3b9b,0x3ad53b79,0x39a13a74,0x38e539f6,0x372c38ab,0x349f3753,0x30be34d5,0xac9c2f0e,0xb153a0b6,0xb6c6b408,0xb76fb51d,0xb9c0b8a6,0xb9bcb8c9,0xbb5cbaaa,
0x3be53c00,0x3bdd3c00,0x3b163b97,0x3acb3b74,0x398b3a65,0x38cc39e5,0x36dd388c,0x344b3710,0x2fbd3475,0xae5f2d7e,0xb263a91b,0xb742b481,0xb7feb5ab,0xb9f8b8e2,0xb9fcb90e,0xbb7fbad9,
0x3be43c00,0x3bdc3c00,0x3b0d3b93,0x3ac13b70,0x39743a56,0x38b239d4,0x368d386d,0x33eb36cc,0x2dfb3414,0xb0102bd9,0xb371ac83,0xb7bdb4f9,0xb845b637,0xba2db91d,0xba39b951,0xbb9ebb05,
0x3be33c00,0x3bda3c00,0x3b043b8f,0x3ab63b6b,0x395d3a47,0x389939c3,0x363c384d,0x33403687,0x2c383365,0xb0f028b6,0xb43eae78,0xb81ab570,0xb889b6c1,0xba60b956,0xba73b992,0xbbb8bb2e,
0x3be23c00,0x3bd93c00,0x3afb3b8a,0x3aac3b67,0x39463a37,0x387f39b1,0x35eb382d,0x32943642,0x28e832a1,0xb1cf2248,0xb4c3b036,0xb855b5e5,0xb8ccb748,0xba90b98d,0xbaa9b9d0,0xbbcfbb53,
0x3c003c00,0x3bfe3c00,0x3c003c00,0x3bf73bfc,0x3c003c00,0x3beb3bf2,0x3c003c00,0x3bd93be3,0x3c003c00,0x3bc13bce,0x3c003c00,0x3ba53bb4,0x3c003c00,0x3b823b94,0x3bff3bff,0x3b5b3b6f,
0x3c003c00,0x3bfe3c00,0x3c003c00,0x3bf53bfb,0x3bff3c00,0x3be63bee,0x3bff3bff,0x3bcf3bdb,0x3bfe3bfe,0x3bb23bc1,0x3bfd3bfe,0x3b8e3ba1,0x3bfc3bfd,0x3b643b7a,0x3bfb3bfb,0x3b333b4c,
0x3c003c00,0x3bfe3c00,0x3bff3c00,0x3bf33bf9,0x3bfe3bff,0x3be03beb,0x3bfd3bfd,0x3bc53bd3,0x3bfb3bfc,0x3ba13bb4,0x3bf83bf9,0x3b753b8c,0x3bf53bf7,0x3b413b5c,0x3bf23bf3,0x3b063b25,
0x3c003c00,0x3bfd3c00,0x3bff3bff,0x3bf03bf8,0x3bfc3bfe,0x3bda3be6,0x3bf93bfb,0x3bb93bca,0x3bf53bf7,0x3b8e3ba5,0x3bf03bf3,0x3b5a3b75,0x3beb3bee,0x3b1c3b3c,0x3be43be7,0x3ad53afa,
0x3c003c00,0x3bfd3c00,0x3bfe3bff,0x3bee3bf7,0x3bfa3bfc,0x3bd33be2,0x3bf53bf8,0x3bac3bc1,0x3bee3bf2,0x3b7a3b94,0x3be63beb,0x3b3c3b5c,0x3bdd3be2,0x3af43b19,0x3bd13bd7,0x3aa13acb,
0x3bff3c00,0x3bfc3c00,0x3bfc3bfe,0x3beb3bf5,0x3bf73bfa,0x3bcb3bdd,0x3bf03bf4,0x3b9e3bb6,0x3be63beb,0x3b643b82,0x3bda3be0,0x3b1c3b41,0x3bcb3bd3,0x3ac83af4,0x3bba3bc3,0x3a683a9a,
0x3bff3c00,0x3bfb3bff,0x3bfb3bfd,0x3be73bf3,0x3bf43bf8,0x3bc33bd7,0x3be93bef,0x3b8f3bab,0x3bdb3be3,0x3b4c3b6f,0x3bca3bd3,0x3afa3b25,0x3bb63bc1,0x3a9a3acb,0x3b9f3bab,0x3a2c3a65,
0x3bff3c00,0x3bfb3bff,0x3bf93bfd,0x3be43bf2,0x3bf03bf5,0x3bba3bd1,0x3be23be9,0x3b7f3b9f,0x3bcf3bd9,0x3b333b5b,0x3bb93bc5,0x3ad53b06,0x3b9e3bac,0x3a683aa1,0x3b7f3b8f,0x39ec3a2c,
0x3bfa3bff,0x3bf33bff,0x3be03bf0,0x3bba3bdc,0x3bb13bcb,0x3b533b8c,0x3b6e3b92,0x3ac33b10,0x3b183b45,0x3a0c3a6c,0x3aaf3ae5,0x393139a3,0x3a343a73,0x383938b9,0x39a939f1,0x36513767,
0x3bf93bff,0x3bf23bfe,0x3bdc3bee,0x3bb43bd9,0x3ba73bc5,0x3b453b82,0x3b5c3b85,0x3aa93afd,0x3afb3b2e,0x39e43a4c,0x3a863ac3,0x38fa3973,0x39fd3a44,0x37e03878,0x396339b2,0x359c36c3,
0x3bf93bff,0x3bf13bfe,0x3bd83beb,0x3bae3bd6,0x3b9d3bbe,0x3b373b78,0x3b493b76,0x3a8f3ae9,0x3add3b16,0x39bb3a2a,0x3a5b3a9f,0x38c03942,0x39c43a12,0x374b3836,0x39193971,0x34e4361d,
0x3bf83bff,0x3bf03bfe,0x3bd33be9,0x3ba73bd3,0x3b923bb6,0x3b273b6e,0x3b353b67,0x3a733ad4,0x3abe3afd,0x39913a08,0x3a2e3a79,0x38853910,0x398839de,0x36b237e6,0x38cd392d,0x34293573,
0x3bf73bff,0x3bee3bfe,0x3bcf3be7,0x3ba13bcf,0x3b873baf,0x3b183b64,0x3b203b57,0x3a573abe,0x3a9d3ae2,0x396539e4,0x39ff3a51,0x384938dc,0x394939a7,0x3617375c,0x387e38e6,0x32d834c6,
0x3bf63bff,0x3bed3bfe,0x3bca3be4,0x3b9a3bcc,0x3b7b3ba6,0x3b073b58,0x3b0a3b47,0x3a3a3aa8,0x3a7b3ac6,0x393939bf,0x39cf3a28,0x380b38a7,0x3908396e,0x357936cf,0x382c389d,0x315a3417,
0x3bf53bff,0x3bec3bfe,0x3bc53be2,0x3b933bc8,0x3b6e3b9e,0x3af73b4d,0x3af43b35,0x3a1c3a91,0x3a573aa9,0x390b399a,0x399c39fd,0x37993871,0x38c53934,0x34d8363f,0x37af3851,0x2fb032cc,
0x3bf43bff,0x3beb3bfe,0x3bbf3bdf,0x3b8c3bc5,0x3b613b95,0x3ae53b41,0x3adc3b23,0x39fd3a79,0x3a323a8b,0x38dc3973,0x396739d1,0x37183839,0x388038f7,0x343535ae,0x37023803,0x2ca93166,
0x3be93bfd,0x3bdd3bfc,0x3b853bc1,0x3b413b9e,0x3ad43b35,0x3a343ac8,0x39de3a61,0x38c53988,0x38ac394b,0x361737e0,0x36963800,0x30863435,0x3322351a,0xaecf2484,0x267b2ffb,0xb590b352,
0x3be83bfd,0x3bdb3bfc,0x3b7d3bbd,0x3b383b99,0x3ac13b29,0x3a1e3ab9,0x39bd3a48,0x389f396a,0x387b3923,0x35a83783,0x3611378e,0x2ecf336b,0x31d53484,0xb0b8a54d,0xa5b22d26,0xb645b45a,
0x3be63bfd,0x3bd93bfc,0x3b753bb9,0x3b2e3b94,0x3aaf3b1c,0x3a083aa9,0x399c3a2e,0x3878394b,0x384938fa,0x35373724,0x358a3718,0x2c903269,0x308633d9,0xb207ab8e,0xac77289d,0xb6f6b508,
0x3be53bfd,0x3bd73bfb,0x3b6d3bb5,0x3b253b8f,0x3a9b3b0f,0x39f13a9a,0x397a3a14,0x3851392d,0x381638cf,0x34c636c3,0x350236a1,0x289d3166,0x2e6b32a7,0xb352ae39,0xaf7ea052,0xb7a4b5b3,
0x3be33bfd,0x3bd53bfb,0x3b653bb0,0x3b1b3b8a,0x3a883b01,0x39d93a8a,0x395739f9,0x3829390d,0x37c538a4,0x34543662,0x34783628,0x12483061,0x2b8e3172,0xb44eb055,0xb141aac5,0xb826b65c,
0x3be23bfd,0x3bd33bfb,0x3b5c3bac,0x3b103b85,0x3a733af4,0x39c13a79,0x393439de,0x380038ed,0x375c3878,0x33c035ff,0x33d935ae,0xa86b2eb6,0x2484303c,0xb4f0b18b,0xb2bfae39,0xb878b702,
0x3be03bfc,0x3bd13bfb,0x3b533ba7,0x3b063b7f,0x3a5f3ae5,0x39a93a68,0x391039c1,0x37af38cd,0x36f1384c,0x32d8359c,0x32bf3531,0xac772ca9,0xa6162e07,0xb590b2bf,0xb41db086,0xb8c8b7a4,
0x3bde3bfc,0x3bcf3bfb,0x3b4b3ba3,0x3afb3b7a,0x3a4a3ad7,0x39913a57,0x38eb39a5,0x375c38ac,0x3684381e,0x31ee3537,0x31a434b4,0xaeb62934,0xac2b2b2a,0xb62eb3f1,0xb4d8b1ee,0xb914b821,
0x3bcd3bfa,0x3bbb3bf8,0x3af03b74,0x3a933b43,0x39783a46,0x38a239b0,0x3707388b,0x344736e0,0x310334d2,0xacdb2e39,0xb07a2052,0xb690b3e5,0xb6c9b490,0xb991b87e,0xb95eb86e,0xbb30ba79,
0x3bcb3bfa,0x3bb93bf8,0x3ae53b6e,0x3a863b3c,0x395e3a34,0x3885399c,0x36b23869,0x33d93696,0x3016346c,0xaeb62c90,0xb197a616,0xb713b472,0xb761b526,0xb9ccb8be,0xb9a5b8b9,0xbb58baad,
0x3bc93bfa,0x3bb63bf8,0x3ada3b68,0x3a793b35,0x39443a22,0x38693988,0x365c3846,0x3322364b,0x2e523405,0xb04829ca,0xb2b3ab2a,0xb793b4f0,0xb7f6b5b9,0xba05b8fc,0xb9e8b901,0xbb7dbadd,
0x3bc73bfa,0x3bb43bf7,0x3acf3b62,0x3a6c3b2e,0x392a3a10,0x384c3973,0x36053824,0x326935ff,0x2c77333a,0xb13424e9,0xb3cdada3,0xb809b56d,0xb844b64b,0xba3cb939,0xba28b947,0xbb9dbb0a,
0x3bc53bf9,0x3bb13bf7,0x3ac33b5c,0x3a5f3b27,0x391039fd,0x382e395e,0x35ae3800,0x31b035b3,0x29343269,0xb21f9f12,0xb472afb0,0xb846b5e8,0xb88bb6da,0xba70b973,0xba65b98a,0xbbb9bb34,
0x3bc23bf9,0x3baf3bf7,0x3ab73b56,0x3a513b20,0x38f539ea,0x38113949,0x355537ba,0x30f63567,0x21e43197,0xb309a839,0xb4fcb0de,0xb883b662,0xb8cfb767,0xbaa1b9ab,0xba9db9ca,0xbbd0bb5a,
0x3bc03bf9,0x3bac3bf7,0x3aab3b50,0x3a443b19,0x38d939d7,0x37e63934,0x34fc3772,0x303c351a,0xa48430c5,0xb3f1ab8e,0xb584b1e2,0xb8beb6da,0xb912b7f1,0xbacfb9e2,0xbad2ba08,0xbbe3bb7c,
0x3bbe3bf9,0x3ba93bf6,0x3a9f3b49,0x3a363b12,0x38be39c4,0x37a9391e,0x34a23729,0x2f0134cc,0xa9fd2fe2,0xb46cad71,0xb60bb2e4,0xb8f7b750,0xb953b83c,0xbafaba16,0xbb03ba42,0xbbf1bb9a,
0x96488000,0xa6ad8000,0x9cb69a48,0xad00aaac,0x9fdb9e48,0xb029aeaa,0xa17fa0b6,0xb1cfb0fd,0xa311a248,0xb371b2a1,0xa452a3db,0xb487b420,0xa51ba4b6,0xb552b4ed,0xa5e4a57f,0xb61ab5b6,
0x9cb68000,0xa7768000,0xa311a0b6,0xad97ab75,0xa5e4a4b6,0xb0a6af72,0xa81fa711,0xb27cb191,0xa94da8b6,0xb426b365,0xaa7aa9e3,0xb50bb499,0xaba7ab11,0xb5ebb57c,0xac6aac1f,0xb6c6b659,
0x9fdb8000,0xa81f8000,0xa5e4a3db,0xae2dac1f,0xa8e8a7da,0xb122b01d,0xaadea9e3,0xb328b226,0xac6aabd9,0xb493b414,0xad65ace7,0xb58db511,0xae5fade2,0xb682b608,0xaf59aedc,0xb76fb6f9,
0xa17f8000,0xa8848000,0xa81fa57f,0xaec3ac83,0xaadea97f,0xb19eb080,0xacceac1f,0xb3d3b2b9,0xae2dad7e,0xb4ffb475,0xaf8baedc,0xb60eb587,0xb074b01d,0xb715b693,0xb122b0cb,0xb80ab796,
0xa3118000,0xa8e88000,0xa94da711,0xaf59ace7,0xac6aab11,0xb219b0e4,0xae2dad4c,0xb43eb34c,0xafefaf0e,0xb56ab4d5,0xb0d7b067,0xb68db5fd,0xb1b6b147,0xb7a6b71b,0xb294b226,0xb85ab817,
0xa4528000,0xa94d8000,0xaa7aa852,0xafefad4c,0xad65ac51,0xb294b147,0xaf8bae78,0xb493b3df,0xb0d7b04e,0xb5d4b534,0xb1e8b160,0xb70ab670,0xb2f7b26f,0xb81ab7a1,0xb402b37d,0xb8a8b862,
0xa51b8000,0xa9b18000,0xaba7a91b,0xb042adb0,0xae5fad1a,0xb30fb1aa,0xb074afa4,0xb4e7b438,0xb1b6b115,0xb63cb593,0xb2f7b257,0xb785b6e3,0xb41ab396,0xb85fb812,0xb4b7b469,0xb8f3b8ab,
0xa5e48000,0xaa168000,0xac6aa9e3,0xb08dae14,0xaf59ade2,0xb389b20d,0xb122b067,0xb53ab481,0xb294b1db,0xb6a4b5f1,0xb402b34c,0xb7feb753,0xb4b7b45d,0xb8a3b852,0xb56ab511,0xb93cb8f1,
0xaa7a8000,0xacce8000,0xb0d7ae78,0xb328b0cb,0xb402b26f,0xb5dfb4bd,0xb58db4c9,0xb805b6f9,0xb70ab64e,0xb902b887,0xb83ab7c2,0xb9e3b976,0xb8e5b891,0xbaa2ba47,0xb982b935,0xbb3abaf3,
0xaade8000,0xad008000,0xb122aedc,0xb371b0fd,0xb43eb2d2,0xb61ab4ed,0xb5dfb511,0xb82ab73d,0xb76fb6aa,0xb92eb8b0,0xb874b817,0xba11b9a4,0xb924b8ce,0xbaceba74,0xb9c5b976,0xbb60bb1d,
0xab438000,0xad338000,0xb16caf40,0xb3bab12e,0xb47bb334,0xb654b51d,0xb631b558,0xb850b780,0xb7d2b705,0xb958b8d8,0xb8adb84d,0xba3db9d0,0xb962b909,0xbaf7baa0,0xba04b9b5,0xbb83bb43,
0xaba78000,0xad658000,0xb1b6afa4,0xb402b160,0xb4b7b396,0xb68db54c,0xb682b59f,0xb874b7c2,0xb81ab75e,0xb982b900,0xb8e5b881,0xba67b9fa,0xb99db943,0xbb1ebac9,0xba41b9f2,0xbba1bb67,
0xac068000,0xad978000,0xb201b004,0xb426b191,0xb4f3b3f7,0xb6c6b57c,0xb6d2b5e5,0xb899b802,0xb84ab7b7,0xb9aab927,0xb91bb8b5,0xba90ba23,0xb9d6b97b,0xbb42baf0,0xba7aba2b,0xbbbcbb86,
0xac388000,0xadc98000,0xb24bb036,0xb44bb1c3,0xb52fb42c,0xb6ffb5ab,0xb721b62b,0xb8bcb822,0xb87ab807,0xb9d2b94d,0xb94fb8e7,0xbab6ba4b,0xba0db9b1,0xbb63bb14,0xbab0ba62,0xbbd2bba2,
0xac6a8000,0xadfb8000,0xb294b067,0xb46fb1f4,0xb56ab45d,0xb737b5da,0xb76fb670,0xb8e0b842,0xb8a8b832,0xb9f8b972,0xb982b918,0xbadbba71,0xba41b9e5,0xbb81bb36,0xbae1ba95,0xbbe3bbbb,
0xac9c8000,0xae2d8000,0xb2deb099,0xb493b226,0xb5a5b48d,0xb76fb608,0xb7bdb6b5,0xb902b862,0xb8d6b85d,0xba1db996,0xb9b3b948,0xbafeba95,0xba73ba17,0xbb9cbb55,0xbb10bac6,0xbbf1bbd0,
0xae5f8000,0xafef8000,0xb4b7b257,0xb5d4b3df,0xb7a6b637,0xb8a8b7a1,0xb924b881,0xba1db96d,0xba41b9ba,0xbb32bab5,0xbb1ebab8,0xbbd6bb93,0xbbb3bb72,0xbbfebbf9,0xbbfabbe1,0xbba9bbe3,
0xae918000,0xb0108000,0xb4dbb288,0xb5f7b408,0xb7ddb665,0xb8c1b7cd,0xb946b8a0,0xba39b989,0xba64b9dc,0xbb4abad0,0xbb3dbad9,0xbbe2bba6,0xbbc8bb8c,0xbbf9bbfe,0xbbffbbee,0xbb8bbbd2,
0xaec38000,0xb0298000,0xb4ffb2b9,0xb61ab420,0xb80ab693,0xb8dbb7f9,0xb966b8bf,0xba54b9a4,0xba85b9fe,0xbb60bae9,0xbb59baf9,0xbbedbbb7,0xbbd9bba4,0xbbf0bc00,0xbc00bbf8,0xbb6abbbe,
0xaef58000,0xb0428000,0xb523b2ea,0xb63cb438,0xb825b6c1,0xb8f3b812,0xb986b8dd,0xba6fb9be,0xbaa5ba1f,0xbb76bb02,0xbb73bb17,0xbbf5bbc7,0xbbe7bbb9,0xbbe4bbff,0xbbfcbbfe,0xbb45bba6,
0xaf278000,0xb05b8000,0xb546b31b,0xb65fb451,0xb840b6ee,0xb90cb828,0xb9a6b8fb,0xba89b9d8,0xbac4ba3f,0xbb89bb1a,0xbb8bbb33,0xbbfbbbd5,0xbbf2bbcb,0xbbd6bbfb,0xbbf4bc00,0xbb1bbb8a,
0xaf598000,0xb0748000,0xb56ab34c,0xb682b469,0xb85ab71b,0xb924b83d,0xb9c5b918,0xbaa2b9f2,0xbae1ba5e,0xbb9cbb30,0xbba1bb4e,0xbbffbbe1,0xbbfabbdb,0xbbc3bbf5,0xbbe7bbfe,0xbaeebb6b,
0xaf8b8000,0xb08d8000,0xb58db37d,0xb6a4b481,0xb874b748,0xb93cb852,0xb9e3b935,0xbababa0b,0xbafeba7c,0xbbacbb46,0xbbb5bb67,0xbc00bbeb,0xbbffbbe8,0xbbaebbec,0xbbd7bbf9,0xbabdbb49,
0xafbd8000,0xb0a68000,0xb5b1b3ae,0xb6c6b499,0xb88eb775,0xb954b867,0xba00b951,0xbad1ba23,0xbb18ba99,0xbbbcbb5a,0xbbc6bb7d,0xbbffbbf3,0xbc00bbf2,0xbb96bbe0,0xbbc2bbf0,0xba89bb22,
0xb0be8000,0xb1858000,0xb6e8b4b1,0xb7f3b570,0xb96bb87c,0xba19b91d,0xbae8ba3b,0xbb7fbae6,0xbbc9bb6e,0xbc00bbdd,0xbbfcbbf9,0xbb8ebbe5,0xbb7abbd1,0xba35bafc,0xba50baf9,0xb820b93e,
0xb0d78000,0xb19e8000,0xb70ab4c9,0xb80ab587,0xb982b891,0xba2db930,0xbafeba52,0xbb8ebaf9,0xbbd6bb80,0xbc00bbe6,0xbbf6bbfd,0xbb76bbda,0xbb5cbbc0,0xba00bad6,0xba15bacc,0xb79bb8fb,
0xb0f08000,0xb1b68000,0xb72cb4e1,0xb81ab59f,0xb999b8a6,0xba41b943,0xbb13ba69,0xbb9cbb0b,0xbbe0bb91,0xbbfebbed,0xbbeebc00,0xbb5cbbcd,0xbb3abbab,0xb9c9baae,0xb9d6ba9c,0xb6f4b8b5,
0xb1098000,0xb1cf8000,0xb74eb4f9,0xb82ab5b6,0xb9afb8ba,0xba54b956,0xbb27ba7f,0xbba9bb1d,0xbbe9bba0,0xbbfbbbf4,0xbbe3bc00,0xbb3fbbbe,0xbb16bb95,0xb990ba83,0xb994ba69,0xb648b86d,
0xb1228000,0xb1e88000,0xb76fb511,0xb83ab5ce,0xb9c5b8ce,0xba67b969,0xbb3aba95,0xbbb5bb2e,0xbbf1bbaf,0xbbf6bbf8,0xbbd7bbfe,0xbb21bbad,0xbaeebb7b,0xb954ba56,0xb94fba33,0xb599b822,
0xb13b8000,0xb2018000,0xb790b529,0xb84ab5e5,0xb9dab8e2,0xba7ab97b,0xbb4cbaaa,0xbbc0bb3e,0xbbf7bbbc,0xbbefbbfc,0xbbc8bbfb,0xbb01bb9b,0xbac4bb5f,0xb916ba27,0xb907b9fa,0xb4e7b7ac,
0xb1538000,0xb2198000,0xb7b2b540,0xb85ab5fd,0xb9f0b8f6,0xba8cb98d,0xbb5ebabf,0xbbcbbb4e,0xbbfcbbc9,0xbbe7bbff,0xbbb7bbf6,0xbadebb86,0xba97bb41,0xb8d6b9f6,0xb8bcb9be,0xb432b710,
0xb16c8000,0xb2328000,0xb7d2b558,0xb86ab614,0xba04b909,0xba9eb99f,0xbb6fbad3,0xbbd4bb5d,0xbbfebbd4,0xbbdebc00,0xbba3bbee,0xbababb70,0xba67bb20,0xb894b9c3,0xb86fb980,0xb2f7b670,
0x98b69248,0xa901a2ad,0x9d7f9bdb,0xadd5ac2b,0xa0529f12,0xb093af7e,0xa1e4a11b,0xb238b166,0xa376a2ad,0xb3d9b309,0xa484a420,0xb4bab454,0xa54da4e9,0xb584b520,0xa616a5b2,0xb64bb5e8,
0x9f1298b6,0xa998a376,0xa420a1e4,0xae84aca9,0xa67ba54d,0xb11cb02f,0xa86ba7a8,0xb2f0b207,0xa998a901,0xb460b3d9,0xaac5aa2f,0xb543b4d2,0xabf2ab5c,0xb622b5b3,0xac90ac44,0xb6fcb690,
0xa1e49bdb,0xaa2fa420,0xa6dfa4e9,0xaf33ad26,0xa966a86b,0xb1a4b09f,0xab5caa61,0xb3a8b2a7,0xaca9ac2b,0xb4d2b454,0xada3ad26,0xb5cbb54f,0xae9dae20,0xb6beb645,0xaf97af1a,0xb7a9b734,
0xa4209d7f,0xaac5a484,0xa8cfa6df,0xafe2ada3,0xab8eaa2f,0xb22cb10f,0xad26ac77,0xb42fb346,0xae84add5,0xb543b4ba,0xafe2af33,0xb651b5cb,0xb09fb048,0xb756b6d4,0xb14db0f6,0xb829b7d5,
0xa54d9f12,0xab5ca4e9,0xaa2fa86b,0xb048ae20,0xacdbabf2,0xb2b3b17f,0xae9dadbc,0xb48ab3e5,0xb02faf7e,0xb5b3b520,0xb10fb09f,0xb6d4b645,0xb1eeb17f,0xb7ebb761,0xb2ccb25d,0xb87bb839,
0xa67ba052,0xabf2a54d,0xab8ea966,0xb09fae9d,0xadeeacdb,0xb33ab1ee,0xb00aaf01,0xb4e4b441,0xb11cb093,0xb622b584,0xb22cb1a4,0xb756b6be,0xb33ab2b3,0xb83eb7eb,0xb423b3c0,0xb8cab885,
0xa7a8a11b,0xac44a5b2,0xac77aa61,0xb0f6af1a,0xaf01adbc,0xb3c0b25d,0xb0c5b023,0xb53db490,0xb207b166,0xb690b5e8,0xb346b2a7,0xb7d5b734,0xb441b3e5,0xb885b839,0xb4deb490,0xb917b8cf,
0xa86ba1e4,0xac90a616,0xad26ab5c,0xb14daf97,0xb00aae9d,0xb423b2cc,0xb17fb0c5,0xb596b4de,0xb2f0b238,0xb6fcb64b,0xb42fb3a8,0xb829b7a9,0xb4e4b48a,0xb8cab87b,0xb596b53d,0xb961b917,
0xacdba67b,0xaf33a8cf,0xb1a4b00a,0xb429b1fa,0xb466b33a,0xb66db54f,0xb5eeb52c,0xb846b783,0xb767b6ad,0xb93db8c5,0xb866b80e,0xba16b9ae,0xb90db8bb,0xbacbba75,0xb9a7b95c,0xbb5abb18,
0xad26a6df,0xaf7ea901,0xb1fab048,0xb454b238,0xb4a8b3a8,0xb6adb584,0xb645b579,0xb86eb7ca,0xb7d0b70d,0xb96ab8f0,0xb8a2b846,0xba44b9db,0xb94eb8fa,0xbaf7baa2,0xb9eab99e,0xbb7ebb40,
0xad71a744,0xafc9a934,0xb251b086,0xb47eb276,0xb4eab40b,0xb6ebb5b9,0xb69bb5c5,0xb895b809,0xb81cb76c,0xb995b919,0xb8dcb87e,0xba70ba08,0xb98cb936,0xbb1fbacd,0xba2ab9de,0xbb9ebb65,
0xadbca7a8,0xb00aa966,0xb2a7b0c5,0xb4a8b2b3,0xb52cb441,0xb729b5ee,0xb6f1b611,0xb8bbb82c,0xb84eb7ca,0xb9bfb942,0xb914b8b4,0xba9aba32,0xb9c8b971,0xbb44baf5,0xba66ba1a,0xbbbabb86,
0xae07a806,0xb02fa998,0xb2fdb103,0xb4d2b2f0,0xb56db478,0xb767b622,0xb745b65c,0xb8e1b84e,0xb880b813,0xb9e8b96a,0xb94bb8e8,0xbac1ba5b,0xba01b9a9,0xbb66bb1b,0xba9fba53,0xbbd1bba3,
0xae52a839,0xb055a9ca,0xb352b141,0xb4fcb32e,0xb5aeb4ae,0xb7a4b656,0xb799b6a7,0xb906b871,0xb8b1b841,0xba10b991,0xb981b91c,0xbae7ba82,0xba38b9e0,0xbb85bb3d,0xbad4ba8a,0xbbe3bbbc,
0xae9da86b,0xb07aa9fd,0xb3a8b17f,0xb526b36b,0xb5eeb4e4,0xb7e0b68a,0xb7ebb6f1,0xb92ab892,0xb8e1b86e,0xba36b9b7,0xb9b4b94e,0xbb0abaa8,0xba6cba14,0xbba0bb5d,0xbb04babc,0xbbf1bbd1,
0xaee8a89d,0xb09faa2f,0xb3fdb1bd,0xb54fb3a8,0xb62eb51a,0xb80eb6be,0xb81eb73a,0xb94eb8b4,0xb910b89a,0xba5bb9db,0xb9e6b97e,0xbb2cbacb,0xba9dba46,0xbbb8bb7b,0xbb31baec,0xbbfbbbe3,
0xb0c5aa61,0xb1eeabf2,0xb579b3e5,0xb6beb4e4,0xb82cb6f1,0xb90db83e,0xb971b8d4,0xba6cb9c8,0xba7fb9ff,0xbb66baf7,0xbb4bbaed,0xbbebbbb8,0xbbcdbb95,0xbbf4bc00,0xbbffbbf0,0xbb80bbca,
0xb0eaaa93,0xb213ac12,0xb5a2b411,0xb6e5b502,0xb849b724,0xb928b856,0xb993b8f5,0xba88b9e4,0xbaa1ba22,0xbb7cbb10,0xbb67bb0d,0xbbf4bbc8,0xbbdebbad,0xbbeabc00,0xbbffbbf9,0xbb5cbbb3,
0xb10faac5,0xb238ac2b,0xb5cbb42f,0xb70db520,0xb866b756,0xb942b86e,0xb9b4b914,0xbaa2b9ff,0xbac1ba44,0xbb90bb29,0xbb81bb2c,0xbbfbbbd6,0xbbebbbc1,0xbbdbbbfc,0xbbfbbbff,0xbb34bb98,
0xb134aaf8,0xb25dac44,0xb5f4b44e,0xb734b53d,0xb883b788,0xb95cb885,0xb9d5b934,0xbabcba1a,0xbae1ba65,0xbba3bb40,0xbb99bb48,0xbbffbbe3,0xbbf6bbd3,0xbbcabbf6,0xbbf2bc00,0xbb07bb7a,
0xb15aab2a,0xb282ac5e,0xb61db46c,0xb75cb55b,0xb89fb7ba,0xb975b89d,0xb9f5b953,0xbad5ba34,0xbafeba84,0xbbb4bb56,0xbbafbb62,0xbc00bbed,0xbbfcbbe2,0xbbb5bbed,0xbbe4bbfd,0xbad7bb57,
0xb17fab5c,0xb2a7ac77,0xb645b48a,0xb783b579,0xb8bbb7eb,0xb98eb8b4,0xba14b971,0xbaedba4e,0xbb1bbaa2,0xbbc3bb6b,0xbbc1bb7b,0xbbffbbf5,0xbc00bbee,0xbb9cbbe1,0xbbd2bbf6,0xbaa2bb31,
0xb1a4ab8e,0xb2ccac90,0xb66db4a8,0xb7a9b596,0xb8d7b80e,0xb9a7b8ca,0xba32b98e,0xbb04ba66,0xbb35bac0,0xbbd1bb7e,0xbbd2bb91,0xbbfbbbfb,0xbbffbbf7,0xbb80bbd2,0xbbbbbbeb,0xba6abb07,
0xb1c9abc0,0xb2f0aca9,0xb696b4c6,0xb7d0b5b3,0xb8f2b826,0xb9bfb8e1,0xba4fb9ab,0xbb1bba7f,0xbb4ebadc,0xbbddbb90,0xbbe0bba6,0xbbf5bbfe,0xbbfcbbfd,0xbb61bbc0,0xbba0bbdd,0xba2ebada,
0xb315acc2,0xb41dad8a,0xb7f6b5d1,0xb890b6b8,0xb9d7b8f7,0xba86b9a0,0xbb30ba96,0xbbb5bb39,0xbbe7bba1,0xbbfabbf6,0xbbecbc00,0xbb4cbbc1,0xbb3fbbab,0xb9bfba9f,0xb9efbaa9,0xb707b8b4,
0xb33aacdb,0xb42fada3,0xb80eb5ee,0xb8a2b6d4,0xb9efb90d,0xba9ab9b4,0xbb44baad,0xbbc1bb4b,0xbbefbbb0,0xbbf5bbfb,0xbbe0bbff,0xbb2dbbaf,0xbb19bb93,0xb983ba72,0xb9abba75,0xb656b869,
0xb35facf4,0xb441adbc,0xb821b60b,0xb8b4b6f1,0xba05b923,0xbaadb9c8,0xbb57bac3,0xbbcdbb5b,0xbbf6bbbe,0xbbeebbfe,0xbbd3bbfd,0xbb0cbb9c,0xbaf0bb78,0xb944ba42,0xb965ba3e,0xb5a2b81c,
0xb383ad0d,0xb454add5,0xb834b628,0xb8c5b70d,0xba1cb939,0xbac0b9db,0xbb69bad9,0xbbd6bb6b,0xbbfbbbcb,0xbbe5bc00,0xbbc2bbf8,0xbae9bb87,0xbac5bb5b,0xb903ba10,0xb91cba03,0xb4eab799,
0xb3a8ad26,0xb466adee,0xb846b645,0xb8d7b729,0xba32b94e,0xbad2b9ef,0xbb7bbaed,0xbbdfbb7a,0xbbfebbd6,0xbbdabc00,0xbbafbbf1,0xbac3bb6f,0xba96bb3b,0xb8c0b9db,0xb8cfb9c6,0xb42fb6f6,
0xb3cdad3f,0xb478ae07,0xb859b662,0xb8e8b745,0xba48b963,0xbae4ba01,0xbb8bbb01,0xbbe7bb88,0xbc00bbe0,0xbbcebbff,0xbb9abbe8,0xba9bbb56,0xba65bb18,0xb87bb9a5,0xb880b985,0xb2e4b651,
0xb3f1ad58,0xb48aae20,0xb86bb67f,0xb8fab761,0xba5db978,0xbaf5ba14,0xbb9abb15,0xbbeebb95,0xbc00bbe9,0xbbc0bbfc,0xbb82bbdd,0xba72bb3b,0xba30baf2,0xb834b96c,0xb82eb942,0xb166b5a8,
0xb40bad71,0xb49cae39,0xb87eb69b,0xb90bb77d,0xba72b98c,0xbb06ba26,0xbba8bb27,0xbbf4bba2,0xbbfebbf0,0xbbb0bbf9,0xbb68bbd0,0xba46bb1d,0xb9f9baca,0xb7d5b931,0xb7b4b8fc,0xafc9b4fc,
0x39b839ba,0x3a973ab5,0x39b339b5,0x3a583a78,0x39af39b1,0x3a153a37,0x39aa39ad,0x39cd39f2,0x39a639a8,0x398239a8,0x39a139a4,0x3933395b,0x399d399f,0x38e03909,0x3999399b,0x388938b5,
0xb979b972,0xb865b832,0xb986b980,0xb8c7b896,0xb994b98d,0xb924b8f6,0xb9a1b99b,0xb97db951,0xb9afb9a8,0xb9d2b9a8,0xb9bcb9b5,0xba21b9fa,0xb9c9b9c3,0xba6bba47,0xb9d6b9d0,0xbab0ba8e,
0xb9f4b9fe,0xbac7bae9,0xb9dfb9e9,0xba7ebaa3,0xb9c9b9d4,0xba2dba56,0xb9b3b9be,0xb9d6ba02,0xb99db9a8,0xb979b9a8,0xb986b992,0xb916b948,0xb970b97b,0xb8adb8e2,0xb958b964,0xb840b877,
0x39373927,0x381a37b7,0x39583948,0x38943858,0x39793969,0x390738ce,0x39993989,0x3974393e,0x39b839a8,0x39da39a8,0x39d639c7,0x3a393a0b,0x39f439e5,0x3a903a65,0x3a113a02,0x3ade3ab8,
0x3a2d3a3f,0x3af43b1a,0x3a093a1b,0x3aa23acc,0x39e339f6,0x3a453a74,0x39bc39d0,0x39df3a13,0x399439a8,0x397039a8,0x396b3980,0x38f83935,0x39413956,0x387a38ba,0x3916392b,0x37e83838,
0xb8f3b8d8,0xb79bb705,0xb929b90e,0xb85fb817,0xb95db943,0xb8eab8a6,0xb990b976,0xb96bb92b,0xb9c0b9a8,0xb9e3b9a8,0xb9f0b9d8,0xba50ba1b,0xba1dba07,0xbab3ba83,0xba49ba33,0xbb0abae0,
0xba64ba7c,0xbb1ebb46,0xba31ba4b,0xbac4baf3,0xb9fcba17,0xba5cba92,0xb9c5b9e1,0xb9e7ba23,0xb98bb9a8,0xb966b9a8,0xb94fb96d,0xb8dbb922,0xb911b930,0xb845b891,0xb8d1b8f1,0xb74eb7ee,
0x38ad3887,0x36ff364e,0x38f838d3,0x382a37ac,0x3941391d,0x38cc387c,0x39863964,0x39623918,0x39c939a8,0x39eb39a8,0x3a0939e9,0x3a673a2b,0x3a453a27,0x3ad53aa0,0x3a7e3a62,0x3b323b05,
0x3b453b6e,0x3bbc3bdd,0x3ae53b17,0x3b573b8f,0x3a733aae,0x3ac73b14,0x39f03a33,0x3a113a71,0x395d39a8,0x393739a8,0x38bc390e,0x384038bf,0x380f3867,0x365f3775,0x36af376a,0x341a3540,
0xb65fb593,0xb389b115,0xb7e8b726,0xb625b4f9,0xb8adb852,0xb830b748,0xb958b905,0xb933b8b5,0xb9f4b9a8,0xba15b9a8,0xba7eba3b,0xbad1ba78,0xbaf4babc,0xbb63bb20,0xbb57bb28,0xbbc6bb9b,
0xbb68bb91,0xbbd0bbed,0xbb04bb39,0xbb6fbba6,0xba89bac9,0xbadbbb2b,0xb9f8ba43,0xba19ba7f,0xb954b9a8,0xb92eb9a8,0xb89eb8fb,0xb820b8ab,0xb7b2b83d,0xb5ebb71b,0xb60eb6e3,0xb2deb4b1,
0x35bc34d5,0x32322f0e,0x377a369e,0x35b13469,0x388e3828,0x380f36ee,0x394f38f1,0x392938a0,0x39fc39a8,0x3a1d39a8,0x3a933a4b,0x3ae53a87,0x3b133ad6,0x3b7a3b36,0x3b783b49,0x3bd93bb1,
0x3b873baf,0x3be13bf8,0x3b213b58,0x3b853bbb,0x3a9e3ae3,0x3aee3b41,0x3a003a52,0x3a213a8e,0x394a39a8,0x392439a8,0x387f38e7,0x37fe3896,0x37423812,0x357636c1,0x356a3659,0x31853420,
0xb517b414,0xb0d7abd9,0xb70ab614,0xb53ab3ae,0xb86fb7f9,0xb7ddb693,0xb946b8dd,0xb91fb88c,0xba04b9a8,0xba25b9a8,0xbaa9ba5a,0xbaf7ba95,0xbb2fbaf0,0xbb90bb4b,0xbb96bb67,0xbbe8bbc4,
0xbba3bbc9,0xbbefbbff,0xbb3dbb74,0xbb9abbcd,0xbab3bafc,0xbb01bb55,0xba09ba62,0xba29ba9c,0xb941b9a8,0xb91bb9a8,0xb85fb8d3,0xb7bdb881,0xb6d2b7cd,0xb4ffb665,0xb4c3b5ce,0xb029b31b,
0x346f32a1,0x2ef52248,0x36993587,0x34c33288,0x385037a1,0x379b3637,0x393c38c9,0x39163877,0x3a0d39a8,0x3a2d39a8,0x3abd3a69,0x3b0a3aa3,0x3b4a3b08,0x3ba33b5f,0x3bb03b82,0x3bf43bd5,
0x3bf83c00,0x3bf93bd4,0x3bac3bdc,0x3be43bfe,0x3b133b69,0x3b543bab,0x3a313aaa,0x3a503ae0,0x391139a8,0x38ea39a8,0x377a386d,0x366b3817,0x34873608,0x313b348d,0x2d9731f4,0xad65291b,
0xac3828b6,0x2ec33365,0xb44bb160,0xb0bea57f,0xb759b5da,0xb648b45d,0xb90cb862,0xb8e5b80d,0xba35b9a8,0xba54b9a8,0xbb1bbab1,0xbb5cbae6,0xbbb5bb72,0xbbe9bbb2,0xbbfcbbe3,0xbbf5bc00,
0xbbfebbfc,0xbbefbbbc,0xbbbdbbe9,0xbbeebc00,0xbb24bb7b,0xbb63bbb9,0xba39bab8,0xba58baed,0xb907b9a8,0xb8e0b9a8,0xb737b858,0xb625b802,0xb40eb5ab,0xb042b42c,0xa9b1b0cb,0x30109a48,
0x25e4ad7e,0xb0beb475,0x33a23036,0x2f8ba3db,0x3715357c,0x360233f7,0x3902384d,0x38db37ee,0x3a3d39a8,0x3a5c39a8,0x3b2c3abf,0x3b6a3af3,0x3bc53b84,0x3bf23bc0,0x3bff3bee,0x3be93c00,
0x3c003bf4,0x3be23ba0,0x3bcc3bf3,0x3bf53bff,0x3b353b8c,0x3b713bc6,0x3a413ac6,0x3a603af9,0x38fd39a8,0x38d639a8,0x36f43842,0x35df37d8,0x3328354c,0x2e913396,0x16482f40,0xb16ca852,
0x251b304e,0x32193534,0xb2adae14,0xad972aac,0xb6d2b51d,0xb5bcb334,0xb8f8b838,0xb8d1b7c2,0xba45b9a8,0xba64b9a8,0xbb3dbacc,0xbb78baff,0xbbd3bb95,0xbbf8bbcb,0xbc00bbf7,0xbbdabbfd,
0xbbfebbe6,0xbbd2bb80,0xbbd9bbfa,0xbbfbbbfb,0xbb45bb9d,0xbb7fbbd1,0xba49bad3,0xba67bb05,0xb8f3b9a8,0xb8ccb9a8,0xb6afb82d,0xb599b7ac,0xb232b4ed,0xac9cb2d2,0x294dace7,0x32c62c83,
0xac06b1db,0xb371b5f1,0x31b62b75,0x2b43adb0,0x368d34bd,0x3576326f,0x38ee3822,0x38c73796,0x3a4d39a8,0x3a6b39a8,0x3b4c3ad9,0x3b853b0b,0x3bdf3ba4,0x3bfd3bd6,0x3bfc3bfd,0x3bc83bf8,
0x3bbd3b5a,0x3b473a99,0x3bfe3bf4,0x3bf93bbe,0x3b8b3bdb,0x3bb83bf7,0x3a6f3b11,0x3a8c3b3e,0x38c139a8,0x389939a8,0x35523780,0x343236cc,0x294d320d,0xad332de2,0xb40eaedc,0xb6a4b408,
0x346336aa,0x36f438b0,0xa6ad3004,0x2e2d3451,0xb52fb1aa,0xb40ead1a,0xb8bcb76a,0xb894b6b5,0xba73b9a8,0xba90b9a8,0xbb92bb17,0xbbbdbb43,0xbbffbbe0,0xbbf6bbf9,0xbbb2bbf0,0xbb35bbb4,
0xbba5bb30,0xbb21ba5e,0xbc00bbeb,0xbbf3bbaa,0xbb98bbe4,0xbbc2bbfb,0xba76bb1d,0xba93bb49,0xb8b7b9a8,0xb88eb9a8,0xb50bb753,0xb3d3b69e,0xa17fb147,0x2f27ac51,0x34b73099,0x37423499,
0xb50bb75e,0xb790b900,0x9cb6b12e,0xb010b4e1,0x34e730e4,0x33892b11,0x38b2373d,0x38893687,0x3a7a39a8,0x3a9739a8,0x3b9e3b22,0x3bc63b4e,0x3c003be8,0x3bef3bfd,0x3b983be5,0x3b0d3b9e,
0x3b893b02,0x3af73a1f,0x3c003bdf,0x3beb3b93,0x3ba33bec,0x3bcb3bfe,0x3a7e3b28,0x3a9b3b53,0x38ad39a8,0x388439a8,0x34c33726,0x33403670,0xa51b3080,0xb08d297f,0xb55eb1c3,0xb7ddb529,
0x35b13807,0x3815394d,0x28843257,0x31093570,0xb49fb01d,0xb2f7a7da,0xb8a8b710,0xb87fb659,0xba81b9a8,0xba9eb9a8,0xbba9bb2e,0xbbcfbb58,0xbbffbbef,0xbbe6bbff,0xbb7abbd7,0xbae1bb86,
0xbb6abad0,0xbacbb9dc,0xbbfdbbd0,0xbbe1bb79,0xbbaebbf2,0xbbd3bc00,0xba85bb33,0xbaa2bb5d,0xb8a3b9a8,0xb87ab9a8,0xb47bb6f9,0xb2adb642,0x2a7aaf72,0x3185a4b6,0x360232ea,0x383a35b6,
0xb654b85d,0xb85fb996,0xac38b37d,0xb201b5fd,0x34572eaa,0x32631e48,0x389e36e3,0x3874362b,0x3a8939a8,0x3aa539a8,0x3bb33b39,0x3bd73b62,0x3bfc3bf5,0x3bdc3c00,0x3b593bc7,0x3ab33b6b,
0x39b739b9,0x3a883aa6,0x39b239b4,0x3a483a68,0x39ae39b0,0x3a033a26,0x39a939ab,0x39bb39e0,0x39a539a7,0x396e3995,0x39a039a3,0x391e3947,0x399c399e,0x38ca38f5,0x3997399a,0x3873389f,
0xb97cb975,0xb87eb84c,0xb98ab983,0xb8deb8ae,0xb997b991,0xb93bb90d,0xb9a5b99e,0xb993b967,0xb9b2b9ab,0xb9e6b9bd,0xb9bfb9b9,0xba34ba0e,0xb9ccb9c6,0xba7dba59,0xb9d9b9d3,0xbac0ba9f,
0xb9efb9f9,0xbab6bad9,0xb9d9b9e4,0xba6aba91,0xb9c4b9cf,0xba18ba42,0xb9aeb9b9,0xb9bfb9ec,0xb997b9a3,0xb961b991,0xb981b98c,0xb8fcb92f,0xb96ab975,0xb892b8c8,0xb953b95e,0xb824b85c,
0x3940392f,0x383937f6,0x39613950,0x38b13876,0x39813971,0x392338eb,0x39a03991,0x398e395a,0x39bf39b0,0x39f339c1,0x39de39cf,0x3a4f3a22,0x39fb39ec,0x3aa43a7b,0x3a183a0a,0x3af03acb,
0x3a243a36,0x3ae13b07,0x39ff3a12,0x3a8b3ab7,0x39d939ec,0x3a2c3a5d,0x39b239c6,0x39c439f9,0x398a399e,0x3953398c,0x39613975,0x38d93917,0x3936394b,0x3859389a,0x390b3921,0x37a43816,
0xb901b8e6,0xb7e6b750,0xb936b91c,0xb883b83c,0xb96ab950,0xb90bb8c8,0xb99cb983,0xb98ab94b,0xb9ccb9b4,0xb9ffb9c6,0xb9fbb9e4,0xba6aba36,0xba28ba12,0xbacaba9b,0xba53ba3e,0xbb1dbaf5,
0xba57ba70,0xbb09bb33,0xba24ba3e,0xbaabbadc,0xb9efba0a,0xba40ba77,0xb9b7b9d3,0xb9c8ba05,0xb97cb99a,0xb944b988,0xb940b95e,0xb8b6b8fe,0xb901b921,0xb81eb86b,0xb8c0b8e1,0xb6fcb79e,
0x38c0389a,0x375636a7,0x390b38e6,0x38543800,0x3953392f,0x38f238a4,0x39973975,0x3985393d,0x39d939b9,0x3a0c39ca,0x3a1839f9,0x3a843a4a,0x3a533a36,0x3aed3abb,0x3a8b3a70,0x3b473b1c,
0x3b2e3b5a,0x3ba63bce,0x3aca3afe,0x3b373b74,0x3a533a91,0x3a9d3aef,0x39cc3a12,0x39de3a42,0x39363983,0x38fc3971,0x389238e6,0x37fb3880,0x37c5383c,0x35d136eb,0x3651370d,0x330934ae,
0xb6c3b5fa,0xb460b251,0xb824b788,0xb6b8b590,0xb8d9b880,0xb873b7d5,0xb981b92f,0xb96eb8f5,0xba18b9cf,0xba48b9e0,0xba9dba5d,0xbafabaa6,0xbb0fbad9,0xbb80bb43,0xbb6cbb40,0xbbd8bbb2,
0xbb51bb7d,0xbbbdbbe0,0xbae7bb1f,0xbb4ebb8c,0xba66baa9,0xbaafbb04,0xb9d1ba1e,0xb9e2ba4e,0xb928b97e,0xb8edb96c,0xb86eb8cd,0xb7afb866,0xb74bb80b,0xb54fb684,0xb5a2b679,0xb197b411,
0x362e3549,0x338330de,0x37e6370d,0x3651350e,0x38c0385c,0x38593788,0x397c3921,0x396a38e6,0x3a2439d3,0x3a5339e4,0x3ab63a70,0x3b0f3ab7,0x3b2e3af5,0x3b973b5a,0x3b8d3b61,0x3be83bc7,
0x3b703b9c,0x3bd03bef,0x3b033b3d,0x3b653ba2,0x3a793ac1,0x3ac03b19,0x39d53a2a,0x39e63a59,0x3919397a,0x38de3967,0x384938b4,0x3761384c,0x36cf37b4,0x34cc361d,0x34f035e2,0x302332e4,
0xb596b496,0xb244aecf,0xb783b690,0xb5e8b48a,0xb8a7b836,0xb83eb73a,0xb978b912,0xb965b8d7,0xba30b9d7,0xba5fb9e8,0xbacdba82,0xbb23bac8,0xbb4cbb10,0xbbacbb6f,0xbbaabb7f,0xbbf4bbd8,
0xbb8dbbb7,0xbbe0bbf9,0xbb1dbb5a,0xbb7abbb5,0xba8bbad9,0xbad0bb2d,0xb9d9ba36,0xb9eaba65,0xb90bb975,0xb8cfb963,0xb824b89a,0xb713b831,0xb651b750,0xb447b5b3,0xb43bb549,0xad58b1a4,
0x34fc33c0,0x31032bc0,0x371e3611,0x357e3405,0x388d3811,0x382436eb,0x39733903,0x396138c8,0x3a3c39db,0x3a6a39ec,0x3ae43a94,0x3b373ad9,0x3b673b2a,0x3bbe3b83,0x3bc33b9a,0x3bfc3be7,
0x3bed3bff,0x3bff3bea,0x3b8d3bc7,0x3bcc3bf5,0x3ae13b40,0x3b1d3b83,0x39ef3a70,0x39ff3a9b,0x38c0395e,0x3883394b,0x36c33816,0x357e3750,0x33833549,0x2e84332e,0x28cf3061,0xb0aca5b2,
0xaf7ea376,0x29663166,0xb514b2fd,0xb2bfad71,0xb809b69b,0xb734b555,0xb95cb8b9,0xb949b87b,0xba75b9f1,0xbaa1ba01,0xbb49bae9,0xbb8bbb25,0xbbcfbb96,0xbbf9bbd2,0xbc00bbf2,0xbbe3bbfe,
0xbbf6bc00,0xbbfcbbda,0xbb9fbbd6,0xbbd8bbfb,0xbaf0bb52,0xbb2cbb92,0xb9f3ba7b,0xba03baa6,0xb8b1b95a,0xb873b947,0xb673b7f6,0xb52cb718,0xb276b4de,0xac5eb251,0x2052ae39,0x321f2bf2,
0x2cf4a806,0xad3fb2d8,0x34a831ee,0x31e22a93,0x37db364b,0x36fc3502,0x395738a9,0x3944386b,0x3a8039f5,0x3aab3a05,0x3b5b3af8,0x3b993b33,0x3bdd3ba7,0x3bfd3bdd,0x3bff3bfa,0x3bd13bf9,
0x3bfd3bfd,0x3bf53bc6,0x3baf3be3,0x3be23bff,0x3b003b64,0x3b393ba0,0x39f73a86,0x3a083ab0,0x38a23955,0x38633942,0x362237bf,0x34d836e0,0x31663472,0x286b3172,0xaaf82b5c,0xb390ae84,
0xa8cf2cf4,0x2fc93423,0xb43bb0de,0xb103a484,0xb7a4b5fa,0xb6c3b4ae,0xb953b89a,0xb940b85c,0xba8bb9f9,0xbab6ba0a,0xbb6cbb07,0xbba6bb40,0xbbe8bbb7,0xbc00bbe7,0xbbfabbff,0xbbbabbf1,
0xbc00bbf6,0xbbebbbae,0xbbbebbed,0xbbebbc00,0xbb0fbb74,0xbb47bbad,0xb9fbba91,0xba0cbabb,0xb892b950,0xb854b93d,0xb5d1b788,0xb484b6a7,0xb055b405,0x9248b093,0x2e6ba484,0x347e3086,
0x98b6afe2,0xb128b4d8,0x339c2f97,0x3023a420,0x376c35a8,0x368a345a,0x394e388b,0x393b384c,0x3a9639fd,0x3ac03a0e,0x3b7c3b16,0x3bb33b4d,0x3bf23bc5,0x3c003bef,0x3bf03c00,0x3ba03be5,
0x3bde3b91,0x3b8a3af7,0x3bf23bff,0x3c003be3,0x3b533bb9,0x3b823bdf,0x3a103ac5,0x3a203aec,0x38443939,0x38033925,0x342f366d,0x31b03584,0xa8392f65,0xb15a1d7f,0xb531b1c9,0xb7e0b55b,
0x3269358a,0x35a83819,0xae842a61,0x205231e2,0xb651b405,0xb567b15a,0xb936b83c,0xb923b7f6,0xbacaba12,0xbaf0ba22,0xbbbebb5a,0xbbe3bb88,0xbbfdbbf5,0xbbddbc00,0xbb81bbd6,0xbadfbb7c,
0xbbcebb70,0xbb6dbac6,0xbbf8bbfb,0xbbffbbd6,0xbb60bbc4,0xbb8dbbe7,0xba14bacf,0xba24baf5,0xb834b934,0xb7e6b921,0xb3b4b634,0xb103b549,0x2c44ada3,0x326925b2,0x35e23309,0x384135f4,
0xb3a8b63a,0xb63fb869,0x2cc2ad58,0xa89db2f0,0x3617335f,0x352c30ac,0x3931382c,0x391e37d5,0x3ad43a16,0x3afa3a26,0x3bc93b66,0x3bea3b92,0x3bf93bfa,0x3bcf3bff,0x3b5f3bc5,0x3aad3b5d,
0x3bba3b4c,0x3b4d3a93,0x3bfc3bf6,0x3bfd3bc7,0x3b6c3bce,0x3b973bed,0x3a183ad9,0x3a283afe,0x3824392f,0x37c5391c,0x330935fa,0x3055350e,0xae6b2bc0,0xb377aa61,0xb690b423,0xb890b68a,
0x347236e5,0x36d438b6,0xa9fd2f7e,0x2c1233fd,0xb5dcb2b3,0xb4f0affb,0xb92db81c,0xb919b7b4,0xbaddba1a,0xbb03ba2a,0xbbd3bb72,0xbbf0bb9c,0xbbf2bbfe,0xbbbfbbfc,0xbb38bbaf,0xba77bb3c,
0xbba4bb23,0xbb2aba5b,0xbbffbbee,0xbbfabbb6,0xbb77bbd7,0xbba1bbf3,0xba1cbae2,0xba2cbb07,0xb813b92a,0xb7a4b917,0xb25db5bf,0xaf4cb4d2,0x3048a839,0x34412cf4,0x373a34c0,0x38dc371e,
0xb50eb78e,0xb767b901,0x24e9b0d1,0xadd5b484,0x35a23207,0x34b42e9d,0x3928380b,0x39143793,0x3ae73a1e,0x3b0c3a2e,0x3bdb3b7d,0x3bf53ba6,0x3be93c00,0x3bad3bf7,0x3b0d3b97,0x3a3e3b18,
0xb999b996,0xb889b85d,0xb99db99b,0xb8e0b8b5,0xb9a1b99f,0xb933b909,0xb9a6b9a4,0xb982b95b,0xb9aab9a8,0xb9cdb9a8,0xb9afb9ad,0xba15b9f2,0xb9b3b9b1,0xba58ba37,0xb9b8b9b5,0xba97ba78,
0xb9d6b9dc,0xbab0bad0,0xb9c9b9d0,0xba6bba8e,0xb9bcb9c3,0xba21ba47,0xb9afb9b5,0xb9d2b9fa,0xb9a1b9a8,0xb97db9a8,0xb994b99b,0xb924b951,0xb986b98d,0xb8c7b8f6,0xb979b980,0xb865b896,
0x3958394d,0x38403807,0x39703964,0x38ad3877,0x3986397b,0x391638e2,0x399d3992,0x39793948,0x39b339a8,0x39d639a8,0x39c939be,0x3a2d3a02,0x39df39d4,0x3a7e3a56,0x39f439e9,0x3ac73aa3,
0x3a113a1f,0x3ade3b02,0x39f43a02,0x3a903ab8,0x39d639e5,0x3a393a65,0x39b839c7,0x39da3a0b,0x399939a8,0x397439a8,0x39793989,0x3907393e,0x39583969,0x389438ce,0x39373948,0x381a3858,
0xb916b900,0xb7e8b75e,0xb941b92b,0xb87ab838,0xb96bb956,0xb8f8b8ba,0xb994b980,0xb970b935,0xb9bcb9a8,0xb9dfb9a8,0xb9e3b9d0,0xba45ba13,0xba09b9f6,0xbaa2ba74,0xba2dba1b,0xbaf4bacc,
0xba49ba5e,0xbb0abb30,0xba1dba33,0xbab3bae0,0xb9f0ba07,0xba50ba83,0xb9c0b9d8,0xb9e3ba1b,0xb990b9a8,0xb96bb9a8,0xb95db976,0xb8eab92b,0xb929b943,0xb85fb8a6,0xb8f3b90e,0xb79bb817,
0x38d138b0,0x374e36aa,0x391138f1,0x384537ee,0x394f3930,0x38db3891,0x398b396d,0x39663922,0x39c539a8,0x39e739a8,0x39fc39e1,0x3a5c3a23,0x3a313a17,0x3ac43a92,0x3a643a4b,0x3b1e3af3,
0x3a7e3a99,0x3b323b5a,0x3a453a62,0x3ad53b05,0x3a093a27,0x3a673aa0,0x39c939e9,0x39eb3a2b,0x398639a8,0x396239a8,0x39413964,0x38cc3918,0x38f8391d,0x382a387c,0x38ad38d3,0x36ff37ac,
0xb6afb5f1,0xb41ab1db,0xb80fb76a,0xb65fb540,0xb8bcb867,0xb840b775,0xb95db90e,0xb937b8bf,0xb9f0b9a8,0xba11b9a8,0xba73ba33,0xbac7ba71,0xbae5baae,0xbb57bb14,0xbb45bb17,0xbbbcbb8f,
0xbb57bb80,0xbbc6bbe6,0xbaf4bb28,0xbb63bb9b,0xba7ebabc,0xbad1bb20,0xb9f4ba3b,0xba15ba78,0xb958b9a8,0xb933b9a8,0xb8adb905,0xb830b8b5,0xb7e8b852,0xb625b748,0xb65fb726,0xb389b4f9,
0x360e3534,0x32de304e,0x37b236e3,0x35eb34b1,0x389e383d,0x3820371b,0x395438fb,0x392e38ab,0x39f839a8,0x3a1939a8,0x3a893a43,0x3adb3a7f,0x3b043ac9,0x3b6f3b2b,0x3b683b39,0x3bd03ba6,
0x3b783ba0,0x3bd93bf4,0x3b133b49,0x3b7a3bb1,0x3a933ad6,0x3ae53b36,0x39fc3a4b,0x3a1d3a87,0x394f39a8,0x392939a8,0x388e38f1,0x380f38a0,0x377a3828,0x35b136ee,0x35bc369e,0x32323469,
0xb56ab475,0xb185ad7e,0xb742b659,0xb576b420,0xb87fb812,0xb7feb6c1,0xb94ab8e7,0xb924b896,0xba00b9a8,0xba21b9a8,0xba9eba52,0xbaeeba8e,0xbb21bae3,0xbb85bb41,0xbb87bb58,0xbbe1bbbb,
0xbb96bbbc,0xbbe8bbfc,0xbb2fbb67,0xbb90bbc4,0xbaa9baf0,0xbaf7bb4b,0xba04ba5a,0xba25ba95,0xb946b9a8,0xb91fb9a8,0xb86fb8dd,0xb7ddb88c,0xb70ab7f9,0xb53ab693,0xb517b614,0xb0d7b3ae,
0x34c33365,0x302928b6,0x36d235ce,0x34ff331b,0x385f37cd,0x37bd3665,0x394138d3,0x391b3881,0x3a0939a8,0x3a2939a8,0x3ab33a62,0x3b013a9c,0x3b3d3afc,0x3b9a3b55,0x3ba33b74,0x3bef3bcd,
0x3bb03bd4,0x3bf43c00,0x3b4a3b82,0x3ba33bd5,0x3abd3b08,0x3b0a3b5f,0x3a0d3a69,0x3a2d3aa3,0x393c39a8,0x391639a8,0x385038c9,0x379b3877,0x369937a1,0x34c33637,0x346f3587,0x2ef53288,
0xad972248,0x2d6532a1,0xb487b1f4,0xb13ba91b,0xb77ab608,0xb66bb48d,0xb911b86d,0xb8eab817,0xba31b9a8,0xba50b9a8,0xbb13baaa,0xbb54bae0,0xbbacbb69,0xbbe4bbab,0xbbf8bbdc,0xbbf9bbfe,
0xbbfcbbff,0xbbf5bbc9,0xbbb5bbe3,0xbbe9bc00,0xbb1bbb72,0xbb5cbbb2,0xba35bab1,0xba54bae6,0xb90cb9a8,0xb8e5b9a8,0xb759b862,0xb648b80d,0xb44bb5da,0xb0beb45d,0xac38b160,0x2ec3a57f,
0x29b1abd9,0xb010b414,0x340e30cb,0x30421a48,0x373735ab,0x3625342c,0x39073858,0x38e03802,0x3a3939a8,0x3a5839a8,0x3b243ab8,0x3b633aed,0x3bbd3b7b,0x3bee3bb9,0x3bfe3be9,0x3bef3c00,
0x3bff3bf8,0x3be93baf,0x3bc53bee,0x3bf23c00,0x3b2c3b84,0x3b6a3bc0,0x3a3d3abf,0x3a5c3af3,0x390239a8,0x38db39a8,0x3715384d,0x360237ee,0x33a2357c,0x2f8b33f7,0x25e43036,0xb0bea3db,
0x96482f0e,0x316c34d5,0xb328af40,0xae912852,0xb6f4b54c,0xb5dfb396,0xb8fdb842,0xb8d6b7d8,0xba41b9a8,0xba60b9a8,0xbb35bac6,0xbb71baf9,0xbbccbb8c,0xbbf5bbc6,0xbc00bbf3,0xbbe2bbff,
0xbc00bbed,0xbbdabb91,0xbbd3bbf7,0xbbf8bbfd,0xbb3dbb95,0xbb78bbcb,0xba45bacc,0xba64baff,0xb8f8b9a8,0xb8d1b9a8,0xb6d2b838,0xb5bcb7c2,0xb2adb51d,0xad97b334,0x251bae14,0x32192aac,
0xa94db115,0xb2c6b593,0x32322ce7,0x2c9cac83,0x36af34ed,0x359932d2,0x38f3382d,0x38cc37ac,0x3a4939a8,0x3a6739a8,0x3b453ad3,0x3b7f3b05,0x3bd93b9d,0x3bfb3bd1,0x3bfe3bfa,0x3bd23bfb,
0x3bfc3bdd,0x3bc83b6e,0x3bdf3bfd,0x3bfd3bf8,0x3b4c3ba4,0x3b853bd6,0x3a4d3ad9,0x3a6b3b0b,0x38ee39a8,0x38c739a8,0x368d3822,0x35763796,0x31b634bd,0x2b43326f,0xac062b75,0xb371adb0,
0x340e364e,0x36a43887,0xa94d2edc,0x2d333408,0xb552b20d,0xb432ade2,0xb8c1b780,0xb899b6cc,0xba6fb9a8,0xba8cb9a8,0xbb8bbb11,0xbbb8bb3e,0xbbfebbdb,0xbbf9bbf7,0xbbbdbbf4,0xbb47bbbe,
0xbbb2bb46,0xbb35ba7c,0xbbffbbf0,0xbbf6bbb4,0xbb92bbe0,0xbbbdbbf9,0xba73bb17,0xba90bb43,0xb8bcb9a8,0xb894b9a8,0xb52fb76a,0xb40eb6b5,0xa6adb1aa,0x2e2dad1a,0x34633004,0x36f43451,
0xb4b7b705,0xb742b8d8,0x217fb099,0xaf27b499,0x350b3147,0x33d32c51,0x38b73753,0x388e369e,0x3a7639a8,0x3a9339a8,0x3b983b1d,0x3bc23b49,0x3c003be4,0x3bf33bfb,0x3ba53beb,0x3b213baa,
0x3b983b1a,0x3b0d3a3f,0x3c003be5,0x3bef3b9e,0x3b9e3be8,0x3bc63bfd,0x3a7a3b22,0x3a973b4e,0x38b239a8,0x388939a8,0x34e7373d,0x33893687,0x9cb630e4,0xb0102b11,0xb50bb12e,0xb790b4e1,
0x355e37b7,0x37dd3927,0x251b31c3,0x308d3529,0xb4c3b080,0xb340a97f,0xb8adb726,0xb884b670,0xba7eb9a8,0xba9bb9a8,0xbba3bb28,0xbbcbbb53,0xbc00bbec,0xbbebbbfe,0xbb89bbdf,0xbaf7bb93,
0xbb7abae9,0xbae1b9fe,0xbbffbbd7,0xbbe6bb86,0xbba9bbef,0xbbcfbbff,0xba81bb2e,0xba9ebb58,0xb8a8b9a8,0xb87fb9a8,0xb49fb710,0xb2f7b659,0x2884b01d,0x3109a7da,0x35b13257,0x38153570,
0xb602b832,0xb83ab972,0xaa7ab2ea,0xb185b5b6,0x347b2f72,0x32ad24b6,0x38a336f9,0x387a3642,0x3a8539a8,0x3aa239a8,0x3bae3b33,0x3bd33b5d,0x3bfd3bf2,0x3be13c00,0x3b6a3bd0,0x3acb3b79,
0x3b593ab5,0x3ab339ba,0x3bfc3bc7,0x3bdc3b6b,0x3bb33bf5,0x3bd73c00,0x3a893b39,0x3aa53b62,0x389e39a8,0x387439a8,0x345736e3,0x3263362b,0xac382eaa,0xb2011e48,0xb654b37d,0xb85fb5fd,
0xb99ab997,0xb89fb873,0xb99eb99c,0xb8f5b8ca,0xb9a3b9a0,0xb947b91e,0xb9a7b9a5,0xb995b96e,0xb9abb9a9,0xb9e0b9bb,0xb9b0b9ae,0xba26ba03,0xb9b4b9b2,0xba68ba48,0xb9b9b9b7,0xbaa6ba88,
0xb9d3b9d9,0xba9fbac0,0xb9c6b9cc,0xba59ba7d,0xb9b9b9bf,0xba0eba34,0xb9abb9b2,0xb9bdb9e6,0xb99eb9a5,0xb967b993,0xb991b997,0xb90db93b,0xb983b98a,0xb8aeb8de,0xb975b97c,0xb84cb87e,
0x395e3953,0x385c3824,0x3975396a,0x38c83892,0x398c3981,0x392f38fc,0x39a33997,0x39913961,0x39b939ae,0x39ec39bf,0x39cf39c4,0x3a423a18,0x39e439d9,0x3a913a6a,0x39f939ef,0x3ad93ab6,
0x3a0a3a18,0x3acb3af0,0x39ec39fb,0x3a7b3aa4,0x39cf39de,0x3a223a4f,0x39b039bf,0x39c139f3,0x399139a0,0x395a398e,0x39713981,0x38eb3923,0x39503961,0x387638b1,0x392f3940,0x37f63839,
0xb921b90b,0xb816b7a4,0xb94bb936,0xb89ab859,0xb975b961,0xb917b8d9,0xb99eb98a,0xb98cb953,0xb9c6b9b2,0xb9f9b9c4,0xb9ecb9d9,0xba5dba2c,0xba12b9ff,0xbab7ba8b,0xba36ba24,0xbb07bae1,
0xba3eba53,0xbaf5bb1d,0xba12ba28,0xba9bbaca,0xb9e4b9fb,0xba36ba6a,0xb9b4b9cc,0xb9c6b9ff,0xb983b99c,0xb94bb98a,0xb950b96a,0xb8c8b90b,0xb91cb936,0xb83cb883,0xb8e6b901,0xb750b7e6,
0x38e138c0,0x379e36fc,0x39213901,0x386b381e,0x395e3940,0x38fe38b6,0x399a397c,0x39883944,0x39d339b7,0x3a0539c8,0x3a0a39ef,0x3a773a40,0x3a3e3a24,0x3adc3aab,0x3a703a57,0x3b333b09,
0x3a703a8b,0x3b1c3b47,0x3a363a53,0x3abb3aed,0x39f93a18,0x3a4a3a84,0x39b939d9,0x39ca3a0c,0x39753997,0x393d3985,0x392f3953,0x38a438f2,0x38e6390b,0x38003854,0x389a38c0,0x36a73756,
0xb70db651,0xb4aeb309,0xb83cb7c5,0xb6ebb5d1,0xb8e6b892,0xb880b7fb,0xb983b936,0xb971b8fc,0xba12b9cc,0xba42b9de,0xba91ba53,0xbaefba9d,0xbafebaca,0xbb74bb37,0xbb5abb2e,0xbbcebba6,
0xbb40bb6c,0xbbb2bbd8,0xbad9bb0f,0xbb43bb80,0xba5dba9d,0xbaa6bafa,0xb9cfba18,0xb9e0ba48,0xb92fb981,0xb8f5b96e,0xb880b8d9,0xb7d5b873,0xb788b824,0xb590b6b8,0xb5fab6c3,0xb251b460,
0x367935a2,0x34113197,0x380b374b,0x3684354f,0x38cd386e,0x386637af,0x397e3928,0x396c38ed,0x3a1e39d1,0x3a4e39e2,0x3aa93a66,0x3b043aaf,0x3b1f3ae7,0x3b8c3b4e,0x3b7d3b51,0x3be03bbd,
0x3b613b8d,0x3bc73be8,0x3af53b2e,0x3b5a3b97,0x3a703ab6,0x3ab73b0f,0x39d33a24,0x39e43a53,0x3921397c,0x38e6396a,0x385c38c0,0x37883859,0x370d37e6,0x350e3651,0x3549362e,0x30de3383,
0xb5e2b4f0,0xb2e4b023,0xb7b4b6cf,0xb61db4cc,0xb8b4b849,0xb84cb761,0xb97ab919,0xb967b8de,0xba2ab9d5,0xba59b9e6,0xbac1ba79,0xbb19bac0,0xbb3dbb03,0xbba2bb65,0xbb9cbb70,0xbbefbbd0,
0xbb7fbbaa,0xbbd8bbf4,0xbb10bb4c,0xbb6fbbac,0xba82bacd,0xbac8bb23,0xb9d7ba30,0xb9e8ba5f,0xb912b978,0xb8d7b965,0xb836b8a7,0xb73ab83e,0xb690b783,0xb48ab5e8,0xb496b596,0xaecfb244,
0x3549343b,0x31a42d58,0x37503651,0x35b33447,0x389a3824,0x38313713,0x3975390b,0x396338cf,0x3a3639d9,0x3a6539ea,0x3ad93a8b,0x3b2d3ad0,0x3b5a3b1d,0x3bb53b7a,0x3bb73b8d,0x3bf93be0,
0x3b9a3bc3,0x3be73bfc,0x3b2a3b67,0x3b833bbe,0x3a943ae4,0x3ad93b37,0x39db3a3c,0x39ec3a6a,0x39033973,0x38c83961,0x3811388d,0x36eb3824,0x3611371e,0x3405357e,0x33c034fc,0x2bc03103,
0xb061a8cf,0x25b230ac,0xb549b383,0xb32eae84,0xb816b6c3,0xb750b57e,0xb95eb8c0,0xb94bb883,0xba70b9ef,0xba9bb9ff,0xbb40bae1,0xbb83bb1d,0xbbc7bb8d,0xbbf5bbcc,0xbbffbbed,0xbbeabbff,
0xbbf2bc00,0xbbfebbe3,0xbb96bbcf,0xbbd2bbf9,0xbae9bb49,0xbb25bb8b,0xb9f1ba75,0xba01baa1,0xb8b9b95c,0xb87bb949,0xb69bb809,0xb555b734,0xb2fdb514,0xad71b2bf,0xa376af7e,0x31662966,
0x2e39a052,0xabf2b21f,0x34de3276,0x32512c5e,0x37f63673,0x3718352c,0x395a38b1,0x39473873,0x3a7b39f3,0x3aa63a03,0x3b523af0,0x3b923b2c,0x3bd63b9f,0x3bfb3bd8,0x3c003bf6,0x3bda3bfc,
0x3bfa3bff,0x3bf93bd1,0x3ba73bdd,0x3bdd3bfd,0x3af83b5b,0x3b333b99,0x39f53a80,0x3a053aab,0x38a93957,0x386b3944,0x364b37db,0x350236fc,0x31ee34a8,0x2a9331e2,0xa8062cf4,0xb2d8ad3f,
0xab5c2af8,0x2e843390,0xb472b166,0xb172a86b,0xb7bfb622,0xb6e0b4d8,0xb955b8a2,0xb942b863,0xba86b9f7,0xbab0ba08,0xbb64bb00,0xbba0bb39,0xbbe3bbaf,0xbbffbbe2,0xbbfdbbfd,0xbbc6bbf5,
0xbbffbbfa,0xbbf1bbba,0xbbb7bbe8,0xbbe7bc00,0xbb07bb6c,0xbb40bba6,0xb9f9ba8b,0xba0abab6,0xb89ab953,0xb85cb940,0xb5fab7a4,0xb4aeb6c3,0xb0deb43b,0xa484b103,0x2cf4a8cf,0x34232fc9,
0x2484ae6b,0xb086b47e,0x34053055,0x30931248,0x378835d1,0x36a73484,0x39503892,0x393d3854,0x3a9139fb,0x3abb3a0c,0x3b743b0f,0x3bad3b47,0x3bed3bbe,0x3c003beb,0x3bf63c00,0x3bae3beb,
0x3c003bf0,0x3be53ba0,0x3bc53bf2,0x3bef3c00,0x3b163b7c,0x3b4d3bb3,0x39fd3a96,0x3a0e3ac0,0x388b394e,0x384c393b,0x35a8376c,0x345a368a,0x2f97339c,0xa4203023,0xafe298b6,0xb4d8b128,
0x31c93531,0x355b37e0,0xaf652839,0x9d7f315a,0xb66db42f,0xb584b1b0,0xb939b844,0xb925b803,0xbac5ba10,0xbaecba20,0xbbb9bb53,0xbbdfbb82,0xbbffbbf2,0xbbe3bc00,0xbb91bbde,0xbaf7bb8a,
0xbbd6bb81,0xbb7cbadf,0xbbf5bbfd,0xbc00bbdd,0xbb5abbbe,0xbb88bbe3,0xba12baca,0xba22baf0,0xb83cb936,0xb7f6b923,0xb405b651,0xb15ab567,0x2a61ae84,0x31e22052,0x358a3269,0x381935a8,
0xb309b5e2,0xb5f4b841,0x2da3ac44,0xa5b2b269,0x363433b4,0x35493103,0x39343834,0x392137e6,0x3acf3a14,0x3af53a24,0x3bc43b60,0x3be73b8d,0x3bfb3bf8,0x3bd63bff,0x3b703bce,0x3ac63b6d,
0x3bc53b5f,0x3b5d3aad,0x3bfa3bf9,0x3bff3bcf,0x3b663bc9,0x3b923bea,0x3a163ad4,0x3a263afa,0x382c3931,0x37d5391e,0x335f3617,0x30ac352c,0xad582cc2,0xb2f0a89d,0xb63ab3a8,0xb869b63f,
0x34233690,0x368a3890,0xabc02e6b,0x2a613377,0xb5fab309,0xb50eb055,0xb92fb824,0xb91cb7c5,0xbad9ba18,0xbafeba28,0xbbcebb6c,0xbbedbb97,0xbbf6bbfc,0xbbc7bbfd,0xbb4cbbba,0xba93bb4d,
0xbbafbb38,0xbb3cba77,0xbbfebbf2,0xbbfcbbbf,0xbb72bbd3,0xbb9cbbf0,0xba1abadd,0xba2abb03,0xb81cb92d,0xb7b4b919,0xb2b3b5dc,0xaffbb4f0,0x2f7ea9fd,0x33fd2c12,0x36e53472,0x38b636d4,
0xb4c0b73a,0xb71eb8dc,0x2839b048,0xacf4b441,0x35bf325d,0x34d22f4c,0x392a3813,0x391737a4,0x3ae23a1c,0x3b073a2c,0x3bd73b77,0x3bf33ba1,0x3bee3bff,0x3bb63bfa,0x3b233ba4,0x3a5b3b2a,
0x3b973b0d,0x3b183a3e,0x3c003be9,0x3bf73bad,0x3b7d3bdb,0x3ba63bf5,0x3a1e3ae7,0x3a2e3b0c,0x380b3928,0x37933914,0x320735a2,0x2e9d34b4,0xb0d124e9,0xb484add5,0xb78eb50e,0xb901b767,
0xb97239ba,0x39dc3996,0xb8323ab5,0x3ad0385d,0x3927b9fe,0xba1fb94d,0x37b7bae9,0xbb02b807,0xb8d83a3f,0x3a5e3900,0xb7053b1a,0x3b30375e,0x3887ba7c,0xba99b8b0,0x364ebb46,0xbb5ab6aa,
0xb90039dc,0x3a3f3972,0xad7e3be6,0x3bf83115,0x3807ba99,0xbae9b887,0xabd9bc00,0xbbfca248,0xb5f13b30,0x3b6e3705,0x32a13bed,0x3bd4b04e,0x3365bba0,0xbbc9b4d5,0xb593bbaf,0xbb803475,
0xb88739fe,0x3a99394d,0x35f13bbc,0x3b6eb414,0x3593bb1a,0xbb80b75e,0xb8b0bb02,0xba7c37b7,0xaf0e3bc9,0x3bf43365,0x3a1f39dc,0x3927b972,0xb04ebc00,0xbbed2248,0xbb30b85d,0xb7053ab5,
0xb8073a1f,0x3ae93927,0x39fe3a3f,0x394db900,0x31dbbb80,0xbbddb593,0xbb6eb832,0xb5f13ad0,0x31153c00,0x3be62248,0x3bff32a1,0x28b6bbd4,0xb7b7bb91,0xbb023534,0xbba0304e,0x34d53bed,
0xb7053a3f,0x3b303900,0x3bbc375e,0x3414bb1a,0x2248bbc9,0xbc00b365,0xbbdda8b6,0x31db3bff,0x36aa3bd4,0x3b46b2a1,0x3a7cb64e,0xb8b0bb5a,0xba1fba5e,0xb92738d8,0xb7b739fe,0x3b02394d,
0xb5f13a5e,0x3b6e38d8,0x3bd42bd9,0xb2a1bbfc,0xb115bbf4,0xbbe6af0e,0xb9dc375e,0x39723b1a,0x39273b46,0x3a1fb6aa,0x3475bad0,0xbbafb832,0xbb91b887,0xb5343a99,0x34143c00,0x3bbc2248,
0xb4d53a7c,0x3ba038b0,0x3a3fb593,0xb900bb80,0xb534bc00,0xbb912248,0xb4143ab5,0x3bbc385d,0x3a993a5e,0x3887b8d8,0xb5f1bbfc,0xbb6e2bd9,0xbbffb475,0x28b63baf,0x3ad03a1f,0x3832b927,
0xb3653a99,0x3bc93887,0x36aab996,0xbb46b9ba,0xb7b7bbed,0xbb02304e,0x34d53bfc,0x3ba02bd9,0x3b913927,0x3534ba1f,0xbae9ba3f,0xb8073900,0xbb5a28b6,0x364e3bff,0x3bd43115,0xb2a1bbe6,
0xb1153ab5,0x3be6385d,0xa8b6bb6e,0xbbffb5f1,0xb900bbbc,0xba3f3414,0x3a1f3b30,0x3927b705,0x3bfc375e,0x2bd9bb1a,0xbbedb475,0x304e3baf,0xb9ba3593,0x39963b80,0x3887b832,0xba99bad0,
0xad7e3ad0,0x3bf83832,0xb7b7bbff,0xbb0228b6,0xb9febb6e,0xb94d35f1,0x3bed3887,0x304eba99,0x3bd43414,0xb2a1bbbc,0xb9963534,0x39ba3b91,0xb6aa3900,0x3b463a3f,0xb115bba0,0xbbe6b4d5,
0xa2483ae9,0x3c003807,0xba99bb30,0xb8873705,0xbad0bb02,0xb83237b7,0x3b462d7e,0xb6aabbf8,0x3b1a28b6,0xb75ebbff,0xaf0e3a7c,0x3bf438b0,0xabd93ab5,0x3bfc385d,0xba5ebb5a,0xb8d8364e,
0x2bd93b02,0x3bfc37b7,0xbbedb927,0xb04e3a1f,0xbb6eba7c,0xb5f138b0,0x385db6aa,0xbab5bb46,0x39dcb1db,0xb972bbdd,0x38323c00,0x3ad02248,0x34d53bbc,0x3ba03414,0xbbf4b705,0x2f0e3b30,
0x304e3b1a,0x3bed375e,0xbb91b475,0x35343baf,0xbbd4b9dc,0xb2a13972,0x2248ba7c,0xbc00b8b0,0x3832b64e,0xbad0bb5a,0x3b803a99,0x3593b887,0x39003bfc,0x3a3fabd9,0xb9273414,0x3a1f3bbc,
0x32a13b30,0x3bd43705,0xb996304e,0x39ba3bed,0xbbffb927,0xa8b63a1f,0xb832bbf4,0xbad0af0e,0x3475b8b0,0xbbafba7c,0x3ba03593,0xb4d5bb80,0x3ae93b6e,0x3807b5f1,0x2bd93a99,0x3bfc3887,
0x34753b46,0x3baf36aa,0xb4d53832,0x3ba03ad0,0xbbedb85d,0x304e3ab5,0xbb30bb5a,0xb705364e,0x2248b9fe,0xbc00b94d,0x3887b414,0xba99bbbc,0x3be63a1f,0x3115b927,0x39dc3bf4,0x3972af0e,
0x35933b5a,0x3b80364e,0x31153a99,0x3be63887,0xbba0b705,0x34d53b30,0xbbf4b8d8,0x2f0e3a5e,0xb414bb02,0xbbbcb7b7,0xabd9ba1f,0xbbfcb927,0x3bd43832,0xb2a1bad0,0x3c003972,0xa248b9dc,
0x36aa3b6e,0x3b4635f1,0x38b03bdd,0x3a7c31db,0xbb1ab534,0x375e3b91,0xba3fb04e,0x39003bed,0xb807bbaf,0xbae9b475,0xb94dbbf8,0xb9fead7e,0x3ab53365,0xb85dbbc9,0x39ba28b6,0xb996bbff,
0x37b73b80,0x3b023593,0x3b1a3bc9,0x375eb365,0xba5eb2a1,0x38d83bd4,0xb53435f1,0x3b913b6e,0xb9babbfc,0xb996abd9,0xbbddbae9,0xb1db3807,0x38b0ad7e,0xba7cbbf8,0x28b6b900,0xbbffba3f,
0x385d3b91,0x3ab53534,0x3c003a5e,0x2248b8d8,0xb972ad7e,0x39dc3bf8,0x33653a3f,0x3bc93900,0xbb02bbe6,0xb7b73115,0xbb1ab6aa,0x375e3b46,0x3414b64e,0xbbbcbb5a,0xb94dbbdd,0xb9feb1db,
0x38d83ba0,0x3a5e34d5,0x3b3037b7,0xb705bb02,0xb85d28b6,0x3ab53bff,0x39ba3be6,0x39963115,0xbbc9bb6e,0xb36535f1,0xb6aa31db,0x3b463bdd,0xaf0eb94d,0xbbf4b9fe,0xbbf8bae9,0xad7e3807,
0x394d3baf,0x39fe3475,0x38d82d7e,0xba5ebbf8,0xb64e3115,0x3b5a3be6,0x3bd43b80,0x32a1b593,0xbbffba99,0x28b63887,0x336539ba,0x3bc93996,0xb75ebae9,0xbb1ab807,0xba3fb534,0x39003b91,
0x39ba3bbc,0x39963414,0x31dbb534,0xbbddbb91,0xb3653475,0x3bc93baf,0x3b803927,0xb593ba1f,0xbba0b972,0x34d539dc,0x3a3f3be6,0x39003115,0xb9febbd4,0xb94db2a1,0xb04e35f1,0x3bed3b6e,
0x3a1f3bc9,0x39273365,0xb475b972,0xbbafb9dc,0xabd9364e,0x3bfc3b5a,0x38d831db,0xba5ebbdd,0xbab5b807,0x385d3ae9,0x3c003b30,0x2248b705,0xbb80bbf4,0xb5932f0e,0x38b03b1a,0x3a7c375e,
0x3a7c3bd4,0x38b032a1,0xb972bb5a,0xb9dcb64e,0x2f0e3807,0x3bf43ae9,0x2d7eb534,0xbbf8bb91,0xb94db4d5,0x39fe3ba0,0x3a5e37b7,0xb8d8bb02,0xbc00bb46,0x224836aa,0x3bdd3bc9,0x31dbb365,
0x3ad03bdd,0x383231db,0xbb80bc00,0xb5932248,0x347538d8,0x3baf3a5e,0xb75eb9fe,0xbb1ab94d,0xb705ad7e,0x3b303bf8,0x3414af0e,0xbbbcbbf4,0xbb6eb9dc,0x35f13972,0x3ab538b0,0xb85dba7c,
0x3b1a3be6,0x375e3115,0xbbf4bb46,0x2f0e36aa,0x37053996,0x3b3039ba,0xbae9bbd4,0xb807b2a1,0xb1db304e,0x3bdd3bed,0xb64eb94d,0xbb5ab9fe,0xb9dcb7b7,0x39723b02,0x3365ad7e,0xbbc9bbf8,
0x3b5a3bed,0x364e304e,0xbab5b94d,0x385d39fe,0x38b03a3f,0x3a7c3900,0xbbffbba0,0x28b634d5,0x2d7e3593,0x3bf83b80,0xbb02bbc9,0xb7b7b365,0xb705b1db,0x3b303bdd,0xb807b9ba,0xbae9b996,
0x3b913bf4,0x35342f0e,0xb807b4d5,0x3ae93ba0,0x39ba3ad0,0x39963832,0xba99b972,0x388739dc,0x3593385d,0x3b803ab5,0xbbe6bb6e,0x311535f1,0xad7e304e,0x3bf83bed,0xbbafbbfc,0xb475abd9,
0x3bbc3bf8,0x34142d7e,0xabd92f0e,0x3bfc3bf4,0x3a993b46,0x388736aa,0xb64eb365,0x3b5a3bc9,0x38b039ba,0x3a7c3996,0xb972b85d,0x39dc3ab5,0x34753705,0x3baf3b30,0xbb1aba5e,0x375e38d8,
0x3bdd3bfc,0x31db2bd9,0x364e3807,0x3b5a3ae9,0x3b463ba0,0x36aa34d5,0x31153475,0x3be63baf,0x3a3f3ad0,0x39003832,0xad7e28b6,0x3bf83bff,0x38d83996,0x3a5e39ba,0xb534b2a1,0x3b913bd4,
0x3bf43bff,0x2f0e28b6,0x3a1f3a7c,0x392738b0,0x3bbc3bdd,0x341431db,0x394d39ba,0x39fe3996,0x3b5a3b91,0x364e3534,0x385d38d8,0x3ab53a5e,0x3ad03b1a,0x3832375e,0x36aa37b7,0x3b463b02,
0x3bff3c00,0x28b62248,0x3bc93bd4,0x336532a1,0x3bf83bfc,0x2d7e2bd9,0x3baf3bbc,0x34753414,0x3bed3bf4,0x304e2f0e,0x3b913ba0,0x353434d5,0x3bdd3be6,0x31db3115,0x3b6e3b80,0x35f13593,
0xb5933b6e,0x3b8035f1,0xb1153bdd,0x3be631db,0x34d5bb91,0xbba0b534,0x2f0ebbed,0xbbf4b04e,0xb4143baf,0x3bbc3475,0xabd93bf8,0x3bfc2d7e,0x32a1bbc9,0xbbd4b365,0x2248bbff,0xbc00a8b6,
0x37b73b46,0x3b02b6aa,0x3b1a3832,0x375ebad0,0xb8d8bab5,0xba5e385d,0xbb91b64e,0xb5343b5a,0x39ba39fe,0x3996b94d,0x3bdd3414,0x31dbbbbc,0xba7cb927,0xb8b03a1f,0xbbffaf0e,0xa8b63bf4,
0x3bd43534,0x32a1bb91,0x39bab8d8,0xb996ba5e,0xbbffad7e,0x28b63bf8,0xb8323a3f,0x3ad03900,0x3bafb115,0xb475bbe6,0x34d5bb46,0xbba0b6aa,0xbae9364e,0x38073b5a,0xabd93bdd,0x3bfc31db,
0x3a5eb75e,0xb8d8bb1a,0xb705bbaf,0xbb303475,0xb85d39dc,0x3ab53972,0x39ba3a7c,0x3996b8b0,0x3365bb5a,0xbbc9b64e,0xbb46b887,0xb6aa3a99,0x2f0e3bfc,0x3bf42bd9,0x3bf83414,0x2d7ebbbc,
0x2bd9bbaf,0xbbfcb475,0xbbedad7e,0x304e3bf8,0x35f13be6,0x3b6eb115,0x3ab5b593,0xb85dbb80,0xb9dcba99,0xb9723887,0xb83239ba,0x3ad03996,0x3ba03807,0x34d5bae9,0x2f0ebb91,0xbbf4b534,
0xb9babae9,0xb9963807,0xb1db3b30,0x3bdd3705,0x3bc937b7,0x3365bb02,0xb593bbf8,0xbb802d7e,0xbba028b6,0x34d53bff,0x3a3f3a7c,0x3900b8b0,0x394db85d,0xb9febab5,0xbbedb64e,0xb04e3b5a,
0xbbf8b365,0x2d7e3bc9,0x3b0239dc,0x37b7b972,0x39feb64e,0xb94dbb5a,0xbbedb1db,0x304e3bdd,0xb2a13ae9,0x3bd43807,0x39bab705,0xb996bb30,0xb6aabbf4,0xbb462f0e,0xb1153b1a,0x3be6375e,
0xb8b0385d,0x3a7c3ab5,0x39dcb5f1,0xb972bb6e,0xaf0ebbbc,0xbbf4b414,0xad7e3b30,0x3bf83705,0x39fe3b1a,0x394db75e,0xb8d8bbaf,0xba5e3475,0xbc00b593,0x22483b80,0x3bdd3832,0x31dbbad0,
0x33653bdd,0x3bc931db,0xb6aabc00,0xbb462248,0xbb02ba5e,0xb7b738d8,0x3ba0394d,0x34d5b9fe,0x3b912d7e,0xb534bbf8,0xbae92f0e,0x38073bf4,0xb64e3972,0x3b5a39dc,0x32a1ba7c,0xbbd4b8b0,
0x3b1a3a7c,0x375eb8b0,0xbbf4b593,0x2f0e3b80,0xbb30a248,0x37053c00,0x3807b85d,0xbae9bab5,0x31dbba5e,0xbbddb8d8,0x364e3bfc,0x3b5a2bd9,0x39723baf,0x39dcb475,0xbbc9b927,0xb3653a1f,
0x3b6e304e,0xb5f1bbed,0xb2a139fe,0x3bd4394d,0xb1153a3f,0x3be63900,0xb9dcbba0,0xb97234d5,0xba1fbb80,0xb9273593,0x3baf3365,0xb475bbc9,0x3b9131db,0xb534bbdd,0xb41439ba,0x3bbc3996,
0x3534b900,0xbb91ba3f,0x3ae93b1a,0x3807b75e,0x39ba3bc9,0x3996b365,0xba9928b6,0x38873bff,0xbb80b2a1,0x35933bd4,0xb115bb5a,0xbbe6b64e,0x2d7eba5e,0xbbf8b8d8,0x3baf39fe,0x3475b94d,
0xb807bbf8,0xbae9ad7e,0x39feaf0e,0xb94dbbf4,0x3bdd36aa,0xb1dbbb46,0x35f13bc9,0x3b6e3365,0xb11539ba,0x3be63996,0xbbffb85d,0x28b63ab5,0xbb02bb30,0xb7b73705,0x34d5b8d8,0xbba0ba5e,
0xbbddb9fe,0xb1db394d,0xb64ebbbc,0xbb5ab414,0x36aab75e,0xbb46bb1a,0x3be637b7,0xb115bb02,0x3a3f3bc9,0x3900b365,0xad7e39dc,0x3bf83972,0xba5ea248,0x38d83c00,0xbb91bab5,0xb534385d,
0xba3fa8b6,0x39003bff,0xbbf8b8b0,0x2d7e3a7c,0xb807bbdd,0xbae9b1db,0x2bd9b9ba,0xbbfcb996,0x3b6e3534,0xb5f1bb91,0x3bd43a5e,0x32a1b8d8,0x33653b1a,0x3bc9375e,0xb59337b7,0x3b803b02,
0xa8b63996,0x3bff39ba,0xb365385d,0x3bc93ab5,0xbbf8b9fe,0xad7e394d,0xbbafbae9,0xb4753807,0x304eb900,0xbbedba3f,0x3534b75e,0xbb91bb1a,0x3bdd3a7c,0x31dbb8b0,0x3b6e3b46,0x35f1b6aa,
0x39dc3c00,0x3972a248,0x3ad03bd4,0x3832b2a1,0xb9272bd9,0x3a1f3bfc,0xb7b73414,0x3b023bbc,0xba5ebbf4,0xb8d82f0e,0xbb30bba0,0xb70534d5,0x3887b115,0xba99bbe6,0x364eb593,0xbb5abb80,
0x3bf43972,0xaf0eb9dc,0x3a1f3115,0xb927bbe6,0x34143a99,0x3bbc3887,0x39fe3c00,0x394d2248,0xbb5ab705,0x364e3b30,0xb85d304e,0x3ab53bed,0xb832bba0,0xbad0b4d5,0xbb46bbaf,0xb6aa3475,
0x3887abd9,0xba99bbfc,0xb5f1bae9,0xbb6eb807,0x3b803ba0,0x3593b4d5,0x3a7c3475,0xb8b0bbaf,0xaf0e3832,0x3bf43ad0,0x3a1f3bff,0x392728b6,0xbbedb996,0x304e39ba,0xb70532a1,0x3b303bd4,
0xb414ba1f,0xbbbcb927,0xbbfcba3f,0x2bd93900,0x3a993593,0xb887bb80,0xb64ebad0,0xbb5ab832,0x3a7c3c00,0x38b02248,0x39dc32a1,0xb972bbd4,0xb4753534,0x3baf3b91,0x3b1a3bed,0x375eb04e,
0xbb30bbf4,0xb7052f0e,0xb41434d5,0x3bbc3ba0,0x2248b832,0xbc00bad0,0xbbddb9dc,0x31db3972,0x3b46385d,0xb6aabab5,0xb8b0bb6e,0xba7cb5f1,0x3a1f3bed,0x3927304e,0x37b7abd9,0xbb02bbfc,
0xbb5ab8d8,0x364e3a5e,0x3ab53bfc,0x385d2bd9,0xba7cbbf4,0xb8b0af0e,0xa8b6375e,0x3bff3b1a,0x2d7eb6aa,0xbbf8bb46,0xbb02b832,0x37b73ad0,0x3b303887,0xb705ba99,0xbae9bc00,0xb807a248,
0xb4d53115,0x3ba03be6,0x3a3f36aa,0xb900bb46,0xbb91b996,0x353439ba,0x3bbc3bd4,0x3414b2a1,0xba99bbed,0xb887b04e,0x35f139fe,0x3b6e394d,0xa8b6b7b7,0xbbffbb02,0xb832ad7e,0x3ad03bf8,
0x38323a99,0x3ad03887,0xb593b996,0xbb80b9ba,0xb475304e,0x3baf3bed,0x375e2bd9,0xbb1abbfc,0xbb30b927,0x37053a1f,0x3bbc3a3f,0xb414b900,0xbb6ebbff,0xb5f128b6,0x3ab53be6,0x385d3115,
0x3be63bd4,0x3115b2a1,0xbbffbb5a,0x28b6364e,0x39003ae9,0x3a3f3807,0xba1fbb91,0xb927b534,0xabd934d5,0x3bfc3ba0,0xb04eb7b7,0xbbedbb02,0xb9bab6aa,0x39963b46,0x38873365,0xba99bbc9,
0x3a1f3832,0xb927bad0,0xb47528b6,0x3baf3bff,0x3bfc3b6e,0xabd9b5f1,0xba5eb887,0x38d83a99,0x3ab53bbc,0x385d3414,0xbc00bb91,0x22483534,0x35933900,0x3b803a3f,0xba7cbba0,0xb8b0b4d5,
0x2248b414,0xbc00bbbc,0x3a993b91,0x38873534,0x38323475,0xbad0bbaf,0x36aa3927,0x3b463a1f,0x3b1a39dc,0xb75eb972,0xaf0e3115,0x3bf43be6,0x3bfc3bd4,0x2bd9b2a1,0xb8d8b5f1,0x3a5e3b6e,
0xb9febb02,0xb94db7b7,0x3a5e3927,0xb8d8ba1f,0xb64eb8b0,0xbb5aba7c,0x3bd43b46,0xb2a1b6aa,0x28b6b1db,0xbbffbbdd,0x3bc93c00,0x33652248,0x375e3414,0xbb1abbbc,0x3a3f3b30,0x39003705,
0xbbedbba0,0x304e34d5,0xb534b7b7,0xbb91bb02,0xbbd4bbff,0xb2a1a8b6,0x2248b115,0xbc00bbe6,0xbad0bb6e,0xb832b5f1,0x359331db,0xbb80bbdd,0xb900b9fe,0xba3fb94d,0x39273807,0xba1fbae9,
0xb85db705,0x3ab53b30,0xbc00bbed,0x2248304e,0xb9dcb927,0x39723a1f,0xbbc9bbf4,0xb365af0e,0xbb02ba7c,0x37b738b0,0xbb1abb80,0xb75eb593,0xbbbcbb6e,0x341435f1,0xb9feba99,0xb94db887,
0x34753593,0x3baf3b80,0xb4d5b365,0x3ba03bc9,0x304e32a1,0x3bed3bd4,0xb705b5f1,0x3b303b6e,0xa2482bd9,0x3c003bfc,0xb887b807,0x3a993ae9,0xb115ad7e,0x3be63bf8,0xb972b900,0x39dc3a3f,
0x3b463b5a,0x36aa364e,0x3a7c3a99,0x38b03887,0x3b1a3b30,0x375e3705,0x3a3f3a5e,0x390038d8,0x3ae93b02,0x380737b7,0x39fe3a1f,0x394d3927,0x3ab53ad0,0x385d3832,0x39ba39dc,0x39963972,
0x28b63c00,0x3bffa248,0x33653bd4,0x3bc9b2a1,0xad7ebbfc,0xbbf82bd9,0xb475bbbc,0xbbaf3414,0x304e3bf4,0x3bedaf0e,0x35343ba0,0x3b91b4d5,0xb1dbbbe6,0xbbdd3115,0xb5f1bb80,0xbb6e3593,
0x3bf4a8b6,0xaf0ebbff,0x3a1fb8b0,0xb927ba7c,0xbbbc31db,0x34143bdd,0xb94d3996,0x39fe39ba,0x3b5ab534,0xb64ebb91,0x385dba5e,0xbab5b8d8,0xbad0375e,0x38323b1a,0xb6aa3b02,0x3b4637b7,
0xb1dbbbfc,0xbbdd2bd9,0xbb5ab807,0xb64e3ae9,0x36aa3ba0,0x3b46b4d5,0x3be63475,0x3115bbaf,0xb900bad0,0xba3f3832,0xbbf8a8b6,0x2d7e3bff,0x3a5e3996,0x38d8b9ba,0x3b91b2a1,0xb534bbd4,
0xbbbc2d7e,0x34143bf8,0x2bd93bf4,0x3bfc2f0e,0x3a99b6aa,0xb887bb46,0xb64ebbc9,0xbb5a3365,0xb8b03996,0x3a7c39ba,0x39723ab5,0x39dcb85d,0x3475bb30,0xbbafb705,0xbb1ab8d8,0xb75e3a5e,
0x35343bf4,0x3b91af0e,0x3ae9b4d5,0xb807bba0,0xb996bad0,0xb9ba3832,0xb8873972,0x3a9939dc,0x3b80385d,0x3593bab5,0x3115bb6e,0xbbe6b5f1,0xbbf8b04e,0x2d7e3bed,0x34753bfc,0x3bafabd9,
0x3b5ab04e,0xb64ebbed,0xbab5b9fe,0xb85d394d,0xb8b03900,0x3a7c3a3f,0x3bff34d5,0x28b6bba0,0x2d7ebb80,0xbbf8b593,0xbb023365,0x37b73bc9,0x37053bdd,0x3b30b1db,0x3807b996,0xbae9b9ba,
0xb75ebbe6,0xbb1a3115,0xaf0e3b46,0x3bf436aa,0x3b303996,0x3705b9ba,0xb807bbd4,0xbae932a1,0xbbddb04e,0x31db3bed,0x3b5a394d,0x364eb9fe,0x3972b7b7,0xb9dcbb02,0xbbc9ad7e,0x33653bf8,
0xbad031db,0x38323bdd,0x3b802248,0xb593bc00,0x3475ba5e,0xbbafb8d8,0xb75e394d,0x3b1a39fe,0x37053bf8,0x3b30ad7e,0xb414bbf4,0xbbbcaf0e,0xbb6eb972,0xb5f139dc,0x3ab53a7c,0x385db8b0,
0x38b03bd4,0x3a7cb2a1,0xb9dcbb5a,0xb972364e,0xbbf4b807,0xaf0e3ae9,0x3bf83534,0xad7ebb91,0x39feb4d5,0xb94dbba0,0xb8d837b7,0x3a5e3b02,0xa2483b46,0x3c0036aa,0xb1dbbbc9,0xbbddb365,
0x3a1fb365,0xb927bbc9,0xb47539dc,0x3baf3972,0x2bd93b5a,0x3bfc364e,0xb8d8bbdd,0xba5e31db,0xbab5bae9,0xb85d3807,0x3c003705,0xa248bb30,0x3b802f0e,0xb593bbf4,0xb8b0375e,0x3a7c3b1a,
0xb996bbbc,0xb9ba3414,0x3bdd3534,0xb1dbbb91,0x3bc93475,0xb365bbaf,0xb5933927,0x3b803a1f,0xb4d53972,0x3ba039dc,0xb900bbe6,0xba3f3115,0xb94dbbd4,0xb9fe32a1,0x3bed35f1,0xb04ebb6e,
0xb94d3475,0x39fe3baf,0xb8d8bbf8,0xba5e2d7e,0xb64ebbe6,0xbb5ab115,0x3bd43593,0xb2a1bb80,0x3bff3887,0x28b6ba99,0xb3653996,0x3bc939ba,0xb75e3807,0x3b1a3ae9,0xba3fbb91,0xb9003534,
0x3a5e3ba0,0x38d8b4d5,0xb70537b7,0x3b303b02,0xbab5a8b6,0x385d3bff,0xb996bbe6,0xb9ba3115,0xb365bb6e,0xbbc9b5f1,0x3b4631db,0xb6aabbdd,0x3bf4394d,0x2f0eb9fe,0x2d7e3ae9,0x3bf83807,
0x385db534,0xbab5bb91,0x3c0038d8,0xa248ba5e,0x39723bf8,0x39dcad7e,0xb3653900,0x3bc93a3f,0xbb02b115,0x37b73be6,0xbb1abb46,0xb75e36aa,0xb414bb5a,0xbbbcb64e,0x394db1db,0xb9febbdd,
0xbb02bb80,0xb7b73593,0xb75ebbc9,0xbb1ab365,0x38d8b2a1,0xba5ebbd4,0x3b9135f1,0xb534bb6e,0x39963bfc,0x39baabd9,0x31db3ae9,0x3bdd3807,0xba7cad7e,0x38b03bf8,0xbbffb900,0x28b63a3f,
0xb6aa35f1,0x3b463b6e,0xb8b031db,0x3a7c3bdd,0xbb1abb91,0xb75e3534,0xba3fbbed,0xb900304e,0x3807b475,0xbae9bbaf,0x394dad7e,0xb9febbf8,0x3ab53bc9,0x385db365,0x39ba3bff,0x3996a8b6,
0x3b803b5a,0x3593b64e,0x3be63a99,0x3115b887,0xb4d53705,0x3ba03b30,0xaf0e38d8,0x3bf43a5e,0xbbbcbb02,0xb41437b7,0xbbfcba1f,0xabd93927,0x32a1b832,0xbbd4bad0,0x2248b972,0xbc00b9dc,
0x3475b6aa,0xbbafbb46,0xb4d5bad0,0xbba0b832,0x3bed3ab5,0x304eb85d,0x3b30364e,0xb705bb5a,0x2248394d,0x3c0039fe,0x38873bbc,0x3a993414,0xbbe6b927,0x31153a1f,0xb9dcaf0e,0x39723bf4,
0xbbd4bb30,0xb2a13705,0xb9bab04e,0x39963bed,0xa8b6b927,0xbbffba1f,0xbad0bbf4,0xb8322f0e,0x3baf38b0,0xb475ba7c,0x34d5b593,0xbba0bb80,0x38073b6e,0x3ae935f1,0x3bfc3a99,0x2bd9b887,
0xb04e375e,0x3bed3b1a,0x3b913baf,0x3534b475,0xbbd4b972,0x32a139dc,0x224838b0,0x3c003a7c,0xb832bb5a,0xbad0b64e,0xbb80b887,0x35933a99,0x39002bd9,0xba3fbbfc,0xb927bbbc,0xba1fb414,
0x3bfc3b02,0x2bd9b7b7,0xb04eb927,0xbbedba1f,0x35f13a7c,0x3b6e38b0,0x3ab536aa,0xb85dbb46,0xb972b1db,0x39dc3bdd,0x3ad03c00,0x3832a248,0xbba0bbbc,0xb4d53414,0xaf0e3705,0x3bf43b30,
0xa248b807,0xbc00bae9,0xba99b705,0x38873b30,0x3ad037b7,0xb832bb02,0xbb46bbf8,0xb6aa2d7e,0x3b1a3bff,0x375ea8b6,0xaf0eb8b0,0xbbf4ba7c,0x2bd9385d,0x3bfc3ab5,0x3a5e364e,0xb8d8bb5a,
0xbbf8bad0,0x2d7e3832,0x3b023bff,0x37b728b6,0xb94dbb6e,0xb9feb5f1,0x304e3887,0x3bed3a99,0x32a1b414,0xbbd4bbbc,0xb9bab534,0x39963b91,0x3b463900,0xb6aaba3f,0xbbe6bba0,0xb11534d5,
0x3115385d,0x3be63ab5,0x28b6b5f1,0xbbffbb6e,0xb900b414,0x3a3f3bbc,0x3a1f3705,0xb927bb30,0xbbfcbb1a,0x2bd9375e,0x3bed3baf,0x304eb475,0xb9babb80,0xb996b593,0x38873ad0,0x3a993832,
0x3bc93a99,0xb365b887,0xbb46b996,0x36aa39ba,0x3b023bed,0x37b7304e,0xbba0bbfc,0xb4d52bd9,0x35343927,0x3b913a1f,0xb807ba3f,0xbae9b900,0xb64ea8b6,0x3b5a3bff,0x32a1b115,0xbbd4bbe6,
0xb4d5b8b0,0xbba0ba7c,0x3a3f3b80,0x39003593,0x35342248,0xbb91bc00,0x3414385d,0x3bbc3ab5,0x3a9938d8,0xb887ba5e,0xb5f1abd9,0x3b6e3bfc,0x3bff3baf,0x28b6b475,0xbad0b927,0x38323a1f,
0xbb6eba5e,0x35f138d8,0x32a1abd9,0xbbd4bbfc,0xbbe6bbf4,0xb1152f0e,0x3972375e,0xb9dcbb1a,0xba1fbb46,0xb927b6aa,0x3baf3ad0,0xb475b832,0xb534b887,0xbb91ba99,0x3bbc3c00,0x3414a248,
0x37053900,0x3b303a3f,0xbbbcbb1a,0x3414375e,0x22483365,0x3c003bc9,0xbbddbbff,0xb1db28b6,0xb6aab2a1,0x3b463bd4,0xba7cbb5a,0xb8b0b64e,0xba1fb8d8,0x39273a5e,0xb7b7b94d,0xbb02b9fe,
0x3ae93a1f,0xb807b927,0x394d3a3f,0x39fe3900,0x3bdd3b80,0xb1dbb593,0x35f13832,0x3b6e3ad0,0x3be63c00,0x3115a248,0x28b632a1,0x3bff3bd4,0x3b023b91,0x37b73534,0xb4d5b04e,0x3ba03bed,
0xb887b94d,0xba99b9fe,0x35f13414,0xbb6ebbbc,0xb593b75e,0xbb80bb1a,0x38b037b7,0xba7cbb02,0xaf0eb365,0xbbf4bbc9,0x3a1f3972,0xb927b9dc,0x304e2248,0xbbedbc00,0x3b303ab5,0xb705b85d,
0xba3fb9dc,0x39003972,0xbbf8bbe6,0x2d7e3115,0xbae9ba99,0x38073887,0xbbfcbc00,0xabd92248,0xbb6ebb30,0x35f13705,0xbbd4bbed,0xb2a1b04e,0xbbc9bba0,0x336534d5,0xbb80bbaf,0xb593b475,
0x39723996,0x39dc39ba,0x3832385d,0x3ad03ab5,0x3927394d,0x3a1f39fe,0x37b73807,0x3b023ae9,0x38d83900,0x3a5e3a3f,0x3705375e,0x3b303b1a,0x388738b0,0x3a993a7c,0x364e36aa,0x3b5a3b46,
0x36aa3b5a,0x3b46b64e,0x38b03a99,0x3a7cb887,0xb75ebb30,0xbb1a3705,0xb900ba5e,0xba3f38d8,0x38073b02,0x3ae9b7b7,0x394d3a1f,0x39feb927,0xb85dbad0,0xbab53832,0xb996b9dc,0xb9ba3972,
0x3475bb80,0xbbafb593,0xb4d5bbc9,0xbba03365,0xb04e3bd4,0x3bed32a1,0x37053b6e,0x3b30b5f1,0xa248bbfc,0xbc00abd9,0xb887bae9,0xba993807,0x31153bf8,0x3be6ad7e,0x39723a3f,0x39dcb900,
0xbab53705,0x385d3b30,0xa2483bed,0x3c00304e,0x3972b927,0xb9dcba1f,0xb365bbf4,0xbbc92f0e,0xb7b73a7c,0x3b0238b0,0x375e3b80,0x3b1ab593,0x3414bb6e,0xbbbcb5f1,0xb94dba99,0xb9fe3887,
0x3bed34d5,0x304ebba0,0x3534bb02,0xbb91b7b7,0xbbd428b6,0x32a13bff,0x22483be6,0x3c003115,0x3ad0b5f1,0xb832bb6e,0xb593bbdd,0xbb8031db,0xb900394d,0x3a3f39fe,0x39273ae9,0x3a1fb807,
0xb94dbb02,0xb9fe37b7,0xb8d83927,0x3a5e3a1f,0x3b5a38b0,0x364eba7c,0x32a1bb46,0xbbd4b6aa,0xbbffb1db,0x28b63bdd,0x33653c00,0x3bc9a248,0x3b1ab414,0xb75ebbbc,0xb900bb30,0xba3f3705,
0x22483bbc,0x3c003414,0x3a99b534,0xb887bb91,0xb832bbaf,0xbad03475,0xb6aa3a1f,0x3b463927,0x3b1a3972,0x375eb9dc,0xaf0ebbe6,0xbbf4b115,0xbbfcb2a1,0x2bd93bd4,0x38d83b6e,0x3a5eb5f1,
0x3927b832,0xba1fbad0,0xbbafa8b6,0x34753bff,0xabd93b6e,0x3bfc35f1,0x38d8b887,0xba5eba99,0xb85dbbbc,0xbab53414,0xa2483b91,0x3c003534,0x3b803900,0x3593ba3f,0xb8b0bba0,0xba7c34d5,
0xbbe6b2a1,0x31153bd4,0x3bff364e,0x28b6bb5a,0x3900b807,0xba3fbae9,0xba1f3534,0x39273b91,0x2bd93ba0,0x3bfc34d5,0x304ebb02,0xbbedb7b7,0xb9babb46,0xb99636aa,0x38873bc9,0x3a99b365,
0x3ad03a99,0x3832b887,0xbb80b996,0xb59339ba,0xbbafb04e,0x34753bed,0x3b1aabd9,0xb75ebbfc,0x3705b927,0xbb30ba1f,0xb4143a3f,0x3bbc3900,0x35f13bff,0x3b6e28b6,0xb85dbbe6,0xbab53115,
0xb4d5bbe6,0xbba0b115,0x3a3f3b46,0x3900b6aa,0x3b9139ba,0x3534b996,0xbbbcb2a1,0x34143bd4,0xba99304e,0x38873bed,0x35f1b94d,0xbb6eb9fe,0x28b6bb02,0xbbffb7b7,0x38323bf8,0x3ad0ad7e,
0xb64e38d8,0x3b5a3a5e,0xb85dbbfc,0xbab52bd9,0xb8b0bbf4,0xba7c2f0e,0x3bff375e,0xa8b6bb1a,0x3bf836aa,0xad7ebb46,0xb7b73832,0x3b023ad0,0xb7053887,0x3b303a99,0xb807bc00,0xbae92248,
0x3b302f0e,0xb705bbf4,0x34143ba0,0x3bbc34d5,0x22483ad0,0x3c003832,0xbbddb972,0xb1db39dc,0xbb46bab5,0xb6aa385d,0x38b0b5f1,0xba7cbb6e,0x3a1fb04e,0xb927bbed,0x37b73bfc,0x3b022bd9,
0xbbbcba1f,0xb4143927,0x2bd9ba3f,0xbbfcb900,0x3887b593,0xba99bb80,0x3b5a3ad0,0x364eb832,0x38b03c00,0x3a7ca248,0xb97232a1,0x39dc3bd4,0xbbafb534,0x34753b91,0xb75ebbed,0xbb1ab04e,
0x38873bfc,0x3a992bd9,0xb5f13807,0x3b6e3ae9,0xbb80b4d5,0x35933ba0,0xba7cbbaf,0xb8b03475,0xaf0ebad0,0xbbf4b832,0x3a1fa8b6,0xb927bbff,0x3bed39ba,0x304eb996,0x37053bd4,0x3b3032a1,
0x2f0eb972,0xbbf4b9dc,0x3927b115,0xba1fbbe6,0x3bbc3a99,0x3414b887,0x394d3c00,0x39fea248,0xb64e3705,0x3b5a3b30,0xbab5b04e,0x385d3bed,0xbad0bba0,0xb83234d5,0xb6aabbaf,0xbb46b475,
0xb9dca248,0x39723c00,0xbad0b2a1,0x38323bd4,0xb927bbfc,0xba1fabd9,0xb7b7bbbc,0xbb02b414,0x3a5e2f0e,0xb8d8bbf4,0x3b3034d5,0xb705bba0,0x38873be6,0x3a993115,0x364e3b80,0x3b5a3593,
0x3bff3996,0xa8b6b9ba,0x3bc9385d,0xb365bab5,0x2d7e39fe,0x3bf8394d,0x34753ae9,0x3baf3807,0xbbedb900,0x304e3a3f,0xbb91b75e,0x35343b1a,0xb1dbba7c,0xbbddb8b0,0xb5f1bb46,0xbb6eb6aa,
0xba3fbbff,0xb90028b6,0xbbf8ba7c,0xad7e38b0,0x3807b1db,0xbae9bbdd,0xabd9b996,0xbbfcb9ba,0x3b6e3b91,0x35f1b534,0x3bd438d8,0xb2a1ba5e,0xb365375e,0x3bc93b1a,0x35933b02,0x3b8037b7,
0x31db39fe,0x3bdd394d,0x3b5a3bbc,0x364eb414,0xbb46b75e,0x36aa3b1a,0xb11537b7,0x3be63b02,0xb900bbc9,0xba3fb365,0xbbf8b9dc,0x2d7e3972,0x38d8a248,0xba5ebc00,0xb534bab5,0xbb91b85d,
0x3807ad7e,0xbae9bbf8,0xb9febbf4,0xb94daf0e,0x3bdd3b46,0x31dbb6aa,0x35f1b365,0xbb6ebbc9,0x31153996,0x3be639ba,0x3bff3ab5,0x28b6b85d,0xbb02b705,0x37b73b30,0x34d53a5e,0x3ba038d8,
0xbb91b900,0x35343a3f,0x38073b1a,0x3ae9375e,0xb996bbc9,0xb9bab365,0xb887a8b6,0x3a993bff,0x3593b2a1,0xbb80bbd4,0xbbe6bb5a,0xb115364e,0x3bf83a5e,0xad7eb8d8,0xb475b9fe,0xbbafb94d,
0x3b6e3bed,0x35f1b04e,0xb2a1b94d,0xbbd4b9fe,0x31153900,0x3be63a3f,0x39dc34d5,0xb972bba0,0xba1fb593,0x39273b80,0x3baf3bc9,0x3475b365,0xbb91bbdd,0xb53431db,0x34143996,0x3bbc39ba,
0xb75eba7c,0xbb1ab8b0,0xaf0e3593,0x3bf43b80,0x3705a248,0xbb30bc00,0xbae9b85d,0x38073ab5,0x3bdd3a5e,0xb1dbb8d8,0xbb5abbfc,0xb64e2bd9,0x39dc3baf,0x39723475,0xb365b927,0xbbc9ba1f,
0xb36531db,0x3bc93bdd,0x36aa2248,0xbb46bc00,0xbb02b8d8,0x37b73a5e,0x3ba039fe,0xb4d5b94d,0xbb91bbf8,0xb5342d7e,0x3ae93bf4,0x38072f0e,0xb64eb9dc,0xbb5ab972,0x32a138b0,0x3bd43a7c,
0x3a7c385d,0xb8b0bab5,0xb972b5f1,0x39dc3b6e,0x3bf43bbc,0x2f0eb414,0xbbf8bb30,0x2d7e3705,0x394d3b1a,0x39fe375e,0xba5ebbaf,0xb8d8b475,0xa2483593,0x3c003b80,0xb1dbb832,0xbbddbad0,
0xbbf8bbc9,0xad7e3365,0x3b023972,0xb7b7b9dc,0xb9febb5a,0xb94db64e,0x3bed3bdd,0x304eb1db,0xb2a1b807,0xbbd4bae9,0x39ba3b30,0x39963705,0x36aa2f0e,0xbb46bbf4,0x3115375e,0x3be63b1a,
0x39963ae9,0x39ba3807,0xbbddbb30,0x31db3705,0x336537b7,0x3bc93b02,0xbb80bbf8,0xb593ad7e,0xb4d5a8b6,0x3ba03bff,0xb900ba7c,0xba3fb8b0,0xb9feb85d,0x394d3ab5,0xb04eb64e,0xbbedbb5a,
0xabd9b475,0xbbfcbbaf,0x3bed3bf8,0x304ead7e,0x35f13115,0xbb6ebbe6,0x3ab53b80,0x385d3593,0x39dc3887,0xb972ba99,0x38323996,0x3ad039ba,0x3ba03ae9,0xb4d5b807,0x2f0e3534,0x3bf43b91,
0xb8d8b75e,0x3a5e3b1a,0xbb30bbaf,0xb705b475,0xbab5b9dc,0x385d3972,0xb996ba7c,0xb9bab8b0,0xbbc9bb5a,0x3365364e,0xb6aab887,0xbb46ba99,0xbbf4bbfc,0xaf0e2bd9,0xad7eb414,0xbbf8bbbc,
0x3bd43b91,0xb2a1b534,0x39ba3a5e,0x399638d8,0x3bff3bf8,0x28b6ad7e,0x38323900,0x3ad03a3f,0x3baf3be6,0x34753115,0x34d536aa,0x3ba03b46,0x3ae93b5a,0x3807364e,0x2bd931db,0x3bfc3bdd,
0xbb02bb46,0xb7b7b6aa,0xb75eb832,0xbb1abad0,0xba5ebab5,0xb8d8b85d,0xb534b64e,0xbb91bb5a,0xb996b9fe,0xb9bab94d,0xb1dbb414,0xbbddbbbc,0xb8b0b927,0xba7cba1f,0xa8b6af0e,0xbbffbbf4,
0x359335f1,0x3b803b6e,0x311531db,0x3be63bdd,0x34d53534,0x3ba03b91,0x2f0e304e,0x3bf43bed,0x34143475,0x3bbc3baf,0x2bd92d7e,0x3bfc3bf8,0x32a13365,0x3bd43bc9,0x224828b6,0x3c003bff,
0x80000,0x680060,0xc800c0,0x1280120,0xc0004,0x6c0064,0xcc00c4,0x12c0124,0x180010,0x780070,0xd800d0,0x1380130,0x1c0014,0x7c0074,0xdc00d4,0x13c0134,
0x1880180,0x1e801e0,0x2480240,0x2a802a0,0x18c0184,0x1ec01e4,0x24c0244,0x2ac02a4,0x1980190,0x1f801f0,0x2580250,0x2b802b0,0x19c0194,0x1fc01f4,0x25c0254,0x2bc02b4,
0x3080300,0x3680360,0x3c803c0,0x4280420,0x30c0304,0x36c0364,0x3cc03c4,0x42c0424,0x3180310,0x3780370,0x3d803d0,0x4380430,0x31c0314,0x37c0374,0x3dc03d4,0x43c0434,
0x4880480,0x4e804e0,0x5480540,0x5a805a0,0x48c0484,0x4ec04e4,0x54c0544,0x5ac05a4,0x4980490,0x4f804f0,0x5580550,0x5b805b0,0x49c0494,0x4fc04f4,0x55c0554,0x5bc05b4,
0x6080600,0x6680660,0x6c806c0,0x7280720,0x60c0604,0x66c0664,0x6cc06c4,0x72c0724,0x6180610,0x6780670,0x6d806d0,0x7380730,0x61c0614,0x67c0674,0x6dc06d4,0x73c0734,
0x7880780,0x7e807e0,0x8480840,0x8a808a0,0x78c0784,0x7ec07e4,0x84c0844,0x8ac08a4,0x7980790,0x7f807f0,0x8580850,0x8b808b0,0x79c0794,0x7fc07f4,0x85c0854,0x8bc08b4,
0x9080900,0x9680960,0x9c809c0,0xa280a20,0x90c0904,0x96c0964,0x9cc09c4,0xa2c0a24,0x9180910,0x9780970,0x9d809d0,0xa380a30,0x91c0914,0x97c0974,0x9dc09d4,0xa3c0a34,
0xa880a80,0xae80ae0,0xb480b40,0xba80ba0,0xa8c0a84,0xaec0ae4,0xb4c0b44,0xbac0ba4,0xa980a90,0xaf80af0,0xb580b50,0xbb80bb0,0xa9c0a94,0xafc0af4,0xb5c0b54,0xbbc0bb4,
0x280020,0x880080,0xe800e0,0x1480140,0x2c0024,0x8c0084,0xec00e4,0x14c0144,0x240020,0x840080,0xe400e0,0x1440140,0x800024,0xe00084,0x14000e4,0x1a00144,
0x1a801a0,0x2080200,0x2680260,0x2c802c0,0x1ac01a4,0x20c0204,0x26c0264,0x2cc02c4,0x1a401a0,0x2040200,0x2640260,0x2c402c0,0x20001a4,0x2600204,0x2c00264,0x32002c4,
0x3280320,0x3880380,0x3e803e0,0x4480440,0x32c0324,0x38c0384,0x3ec03e4,0x44c0444,0x3240320,0x3840380,0x3e403e0,0x4440440,0x3800324,0x3e00384,0x44003e4,0x4a00444,
0x4a804a0,0x5080500,0x5680560,0x5c805c0,0x4ac04a4,0x50c0504,0x56c0564,0x5cc05c4,0x4a404a0,0x5040500,0x5640560,0x5c405c0,0x50004a4,0x5600504,0x5c00564,0x62005c4,
0x6280620,0x6880680,0x6e806e0,0x7480740,0x62c0624,0x68c0684,0x6ec06e4,0x74c0744,0x6240620,0x6840680,0x6e406e0,0x7440740,0x6800624,0x6e00684,0x74006e4,0x7a00744,
0x7a807a0,0x8080800,0x8680860,0x8c808c0,0x7ac07a4,0x80c0804,0x86c0864,0x8cc08c4,0x7a407a0,0x8040800,0x8640860,0x8c408c0,0x80007a4,0x8600804,0x8c00864,0x92008c4,
0x9280920,0x9880980,0x9e809e0,0xa480a40,0x92c0924,0x98c0984,0x9ec09e4,0xa4c0a44,0x9240920,0x9840980,0x9e409e0,0xa440a40,0x9800924,0x9e00984,0xa4009e4,0xaa00a44,
0xaa80aa0,0xb080b00,0xb680b60,0xbc80bc0,0xaac0aa4,0xb0c0b04,0xb6c0b64,0xbcc0bc4,0xaa40aa0,0xb040b00,0xb640b60,0xbc40bc0,0xb000aa4,0xb600b04,0xbc00b64,0x300bc4,
0x300030,0x900090,0xf000f0,0x1500150,0x900034,0xf00094,0x15000f4,0x1b00154,0x340030,0x940090,0xf400f0,0x1540150,0x900034,0xf00094,0x15000f4,0x1b00154,
0x1b001b0,0x2100210,0x2700270,0x2d002d0,0x21001b4,0x2700214,0x2d00274,0x33002d4,0x1b401b0,0x2140210,0x2740270,0x2d402d0,0x21001b4,0x2700214,0x2d00274,0x33002d4,
0x3300330,0x3900390,0x3f003f0,0x4500450,0x3900334,0x3f00394,0x45003f4,0x4b00454,0x3340330,0x3940390,0x3f403f0,0x4540450,0x3900334,0x3f00394,0x45003f4,0x4b00454,
0x4b004b0,0x5100510,0x5700570,0x5d005d0,0x51004b4,0x5700514,0x5d00574,0x63005d4,0x4b404b0,0x5140510,0x5740570,0x5d405d0,0x51004b4,0x5700514,0x5d00574,0x63005d4,
0x6300630,0x6900690,0x6f006f0,0x7500750,0x6900634,0x6f00694,0x75006f4,0x7b00754,0x6340630,0x6940690,0x6f406f0,0x7540750,0x6900634,0x6f00694,0x75006f4,0x7b00754,
0x7b007b0,0x8100810,0x8700870,0x8d008d0,0x81007b4,0x8700814,0x8d00874,0x93008d4,0x7b407b0,0x8140810,0x8740870,0x8d408d0,0x81007b4,0x8700814,0x8d00874,0x93008d4,
0x9300930,0x9900990,0x9f009f0,0xa500a50,0x9900934,0x9f00994,0xa5009f4,0xab00a54,0x9340930,0x9940990,0x9f409f0,0xa540a50,0x9900934,0x9f00994,0xa5009f4,0xab00a54,
0xab00ab0,0xb100b10,0xb700b70,0xbd00bd0,0xb100ab4,0xb700b14,0xbd00b74,0x380bd4,0xab40ab0,0xb140b10,0xb740b70,0xbd40bd0,0xb100ab4,0xb700b14,0xbd00b74,0x380bd4,
0x380038,0x980098,0xf800f8,0x1580158,0x98003c,0xf8009c,0x15800fc,0x1b8015c,0x3c0038,0x9c0098,0xfc00f8,0x15c0158,0x98003c,0xf8009c,0x15800fc,0x1b8015c,
0x1b801b8,0x2180218,0x2780278,0x2d802d8,0x21801bc,0x278021c,0x2d8027c,0x33802dc,0x1bc01b8,0x21c0218,0x27c0278,0x2dc02d8,0x21801bc,0x278021c,0x2d8027c,0x33802dc,
0x3380338,0x3980398,0x3f803f8,0x4580458,0x398033c,0x3f8039c,0x45803fc,0x4b8045c,0x33c0338,0x39c0398,0x3fc03f8,0x45c0458,0x398033c,0x3f8039c,0x45803fc,0x4b8045c,
0x4b804b8,0x5180518,0x5780578,0x5d805d8,0x51804bc,0x578051c,0x5d8057c,0x63805dc,0x4bc04b8,0x51c0518,0x57c0578,0x5dc05d8,0x51804bc,0x578051c,0x5d8057c,0x63805dc,
0x6380638,0x6980698,0x6f806f8,0x7580758,0x698063c,0x6f8069c,0x75806fc,0x7b8075c,0x63c0638,0x69c0698,0x6fc06f8,0x75c0758,0x698063c,0x6f8069c,0x75806fc,0x7b8075c,
0x7b807b8,0x8180818,0x8780878,0x8d808d8,0x81807bc,0x878081c,0x8d8087c,0x93808dc,0x7bc07b8,0x81c0818,0x87c0878,0x8dc08d8,0x81807bc,0x878081c,0x8d8087c,0x93808dc,
0x9380938,0x9980998,0x9f809f8,0xa580a58,0x998093c,0x9f8099c,0xa5809fc,0xab80a5c,0x93c0938,0x99c0998,0x9fc09f8,0xa5c0a58,0x998093c,0x9f8099c,0xa5809fc,0xab80a5c,
0xab80ab8,0xb180b18,0xb780b78,0xbd80bd8,0xb180abc,0xb780b1c,0xbd80b7c,0x400bdc,0xabc0ab8,0xb1c0b18,0xb7c0b78,0xbdc0bd8,0xb180abc,0xb780b1c,0xbd80b7c,0x400bdc,
0xacc0acc,0xb2c0b2c,0xb8c0b8c,0xbec0bec,0xb2c0acc,0xb8c0b8c,0xbec0b8c,0x500050,0xacc0acc,0xb2c0b2c,0xb8c0b8c,0xbec0bec,0xb2c0b2c,0xb8c0b8c,0xbec0bec,0x500050,
0x94c094c,0x9ac09ac,0xa0c0a0c,0xa6c0a6c,0x9ac094c,0xa0c0a0c,0xa6c0a0c,0xacc0acc,0x94c094c,0x9ac09ac,0xa0c0a0c,0xa6c0a6c,0x9ac09ac,0xa0c0a0c,0xa6c0a6c,0xacc0acc,
0x7cc07cc,0x82c082c,0x88c088c,0x8ec08ec,0x82c07cc,0x88c088c,0x8ec088c,0x94c094c,0x7cc07cc,0x82c082c,0x88c088c,0x8ec08ec,0x82c082c,0x88c088c,0x8ec08ec,0x94c094c,
0x64c064c,0x6ac06ac,0x70c070c,0x76c076c,0x6ac064c,0x70c070c,0x76c070c,0x7cc07cc,0x64c064c,0x6ac06ac,0x70c070c,0x76c076c,0x6ac06ac,0x70c070c,0x76c076c,0x7cc07cc,
0x4cc04cc,0x52c052c,0x58c058c,0x5ec05ec,0x52c04cc,0x58c058c,0x5ec058c,0x64c064c,0x4cc04cc,0x52c052c,0x58c058c,0x5ec05ec,0x52c052c,0x58c058c,0x5ec05ec,0x64c064c,
0x34c034c,0x3ac03ac,0x40c040c,0x46c046c,0x3ac034c,0x40c040c,0x46c040c,0x4cc04cc,0x34c034c,0x3ac03ac,0x40c040c,0x46c046c,0x3ac03ac,0x40c040c,0x46c046c,0x4cc04cc,
0x1cc01cc,0x22c022c,0x28c028c,0x2ec02ec,0x22c01cc,0x28c028c,0x2ec028c,0x34c034c,0x1cc01cc,0x22c022c,0x28c028c,0x2ec02ec,0x22c022c,0x28c028c,0x2ec02ec,0x34c034c,
0x4c004c,0xac00ac,0x10c010c,0x16c016c,0xac004c,0x10c010c,0x16c010c,0x1cc01cc,0x4c004c,0xac00ac,0x10c010c,0x16c016c,0xac00ac,0x10c010c,0x16c016c,0x1cc01cc,
0xac80ac8,0xb280b28,0xb880b88,0xbe80be8,0xb280ac8,0xb880b88,0xbe80b88,0x4c004c,0xac80ac8,0xb280b28,0xb880b88,0xbe80be8,0xb280b28,0xb880b88,0xbe80be8,0x4c004c,
0x9480948,0x9a809a8,0xa080a08,0xa680a68,0x9a80948,0xa080a08,0xa680a08,0xac80ac8,0x9480948,0x9a809a8,0xa080a08,0xa680a68,0x9a809a8,0xa080a08,0xa680a68,0xac80ac8,
0x7c807c8,0x8280828,0x8880888,0x8e808e8,0x82807c8,0x8880888,0x8e80888,0x9480948,0x7c807c8,0x8280828,0x8880888,0x8e808e8,0x8280828,0x8880888,0x8e808e8,0x9480948,
0x6480648,0x6a806a8,0x7080708,0x7680768,0x6a80648,0x7080708,0x7680708,0x7c807c8,0x6480648,0x6a806a8,0x7080708,0x7680768,0x6a806a8,0x7080708,0x7680768,0x7c807c8,
0x4c804c8,0x5280528,0x5880588,0x5e805e8,0x52804c8,0x5880588,0x5e80588,0x6480648,0x4c804c8,0x5280528,0x5880588,0x5e805e8,0x5280528,0x5880588,0x5e805e8,0x6480648,
0x3480348,0x3a803a8,0x4080408,0x4680468,0x3a80348,0x4080408,0x4680408,0x4c804c8,0x3480348,0x3a803a8,0x4080408,0x4680468,0x3a803a8,0x4080408,0x4680468,0x4c804c8,
0x1c801c8,0x2280228,0x2880288,0x2e802e8,0x22801c8,0x2880288,0x2e80288,0x3480348,0x1c801c8,0x2280228,0x2880288,0x2e802e8,0x2280228,0x2880288,0x2e802e8,0x3480348,
0x480048,0xa800a8,0x1080108,0x1680168,0xa80048,0x1080108,0x1680108,0x1c801c8,0x480048,0xa800a8,0x1080108,0x1680168,0xa800a8,0x1080108,0x1680168,0x1c801c8,
0xac40ac4,0xb240b24,0xb840b84,0xbe40be4,0xb240ac4,0xb840b84,0xbe40b84,0x480048,0xac40ac4,0xb240b24,0xb840b84,0xbe40be4,0xb240b24,0xb840b84,0xbe40be4,0x480048,
0x9440944,0x9a409a4,0xa040a04,0xa640a64,0x9a40944,0xa040a04,0xa640a04,0xac40ac4,0x9440944,0x9a409a4,0xa040a04,0xa640a64,0x9a409a4,0xa040a04,0xa640a64,0xac40ac4,
0x7c407c4,0x8240824,0x8840884,0x8e408e4,0x82407c4,0x8840884,0x8e40884,0x9440944,0x7c407c4,0x8240824,0x8840884,0x8e408e4,0x8240824,0x8840884,0x8e408e4,0x9440944,
0x6440644,0x6a406a4,0x7040704,0x7640764,0x6a40644,0x7040704,0x7640704,0x7c407c4,0x6440644,0x6a406a4,0x7040704,0x7640764,0x6a406a4,0x7040704,0x7640764,0x7c407c4,
0x4c404c4,0x5240524,0x5840584,0x5e405e4,0x52404c4,0x5840584,0x5e40584,0x6440644,0x4c404c4,0x5240524,0x5840584,0x5e405e4,0x5240524,0x5840584,0x5e405e4,0x6440644,
0x3440344,0x3a403a4,0x4040404,0x4640464,0x3a40344,0x4040404,0x4640404,0x4c404c4,0x3440344,0x3a403a4,0x4040404,0x4640464,0x3a403a4,0x4040404,0x4640464,0x4c404c4,
0x1c401c4,0x2240224,0x2840284,0x2e402e4,0x22401c4,0x2840284,0x2e40284,0x3440344,0x1c401c4,0x2240224,0x2840284,0x2e402e4,0x2240224,0x2840284,0x2e402e4,0x3440344,
0x440044,0xa400a4,0x1040104,0x1640164,0xa40044,0x1040104,0x1640104,0x1c401c4,0x440044,0xa400a4,0x1040104,0x1640164,0xa400a4,0x1040104,0x1640164,0x1c401c4,
0xac00ac0,0xb200b20,0xb800b80,0xbe00be0,0xb200ac0,0xb800b80,0xbe00b80,0x440044,0xac00ac0,0xb200b20,0xb800b80,0xbe00be0,0xb200b20,0xb800b80,0xbe00be0,0x440044,
0x9400940,0x9a009a0,0xa000a00,0xa600a60,0x9a00940,0xa000a00,0xa600a00,0xac00ac0,0x9400940,0x9a009a0,0xa000a00,0xa600a60,0x9a009a0,0xa000a00,0xa600a60,0xac00ac0,
0x7c007c0,0x8200820,0x8800880,0x8e008e0,0x82007c0,0x8800880,0x8e00880,0x9400940,0x7c007c0,0x8200820,0x8800880,0x8e008e0,0x8200820,0x8800880,0x8e008e0,0x9400940,
0x6400640,0x6a006a0,0x7000700,0x7600760,0x6a00640,0x7000700,0x7600700,0x7c007c0,0x6400640,0x6a006a0,0x7000700,0x7600760,0x6a006a0,0x7000700,0x7600760,0x7c007c0,
0x4c004c0,0x5200520,0x5800580,0x5e005e0,0x52004c0,0x5800580,0x5e00580,0x6400640,0x4c004c0,0x5200520,0x5800580,0x5e005e0,0x5200520,0x5800580,0x5e005e0,0x6400640,
0x3400340,0x3a003a0,0x4000400,0x4600460,0x3a00340,0x4000400,0x4600400,0x4c004c0,0x3400340,0x3a003a0,0x4000400,0x4600460,0x3a003a0,0x4000400,0x4600460,0x4c004c0,
0x1c001c0,0x2200220,0x2800280,0x2e002e0,0x22001c0,0x2800280,0x2e00280,0x3400340,0x1c001c0,0x2200220,0x2800280,0x2e002e0,0x2200220,0x2800280,0x2e002e0,0x3400340,
0x400040,0xa000a0,0x1000100,0x1600160,0xa00040,0x1000100,0x1600100,0x1c001c0,0x400040,0xa000a0,0x1000100,0x1600160,0xa000a0,0x1000100,0x1600160,0x1c001c0,
0x30003000,0x30003000,0x30003000,0x30003000,0x30003000,0x30003000,0x30003000,0x30003000,0x0,0x0,0x0,0x0,0x0,0x0,0x0,0x0,
0x30003000,0x30003000,0x30003000,0x30003000,0x30003000,0x30003000,0x30003000,0x30003000,0x0,0x0,0x0,0x0,0x0,0x0,0x0,0x0,
0x2a1f2da8,0xaf64ada8,0xaa1fada8,0x2f642da8,0x2f643000,0xaa1f0000,0xaf64b000,0x2a1f8000,0x2f642da8,0x2a1f2da8,0xaf64ada8,0xaa1fada8,0x2a1f0000,0x2f643000,0xaa1f0000,0xaf64b000,
0x263e2c72,0xafd9aea7,0xa63eac72,0x2fd92ea7,0x2ea72fd9,0xac72a63e,0xaea7afd9,0x2c72263e,0x2fd92ea7,0x263e2c72,0xafd9aea7,0xa63eac72,0x2c72263e,0x2ea72fd9,0xac72a63e,0xaea7afd9,
0x2da80000,0xada80000,0x2da88000,0xada80000,0x2da83000,0xada8b000,0x2da83000,0xada8b000,0x2da83000,0xada8b000,0x2da83000,0xada8b000,0xada80000,0x2da88000,0xada80000,0x2da88000,
0x2f642a1f,0xaf64aa1f,0x2f642a1f,0xaf64aa1f,0x2a1f2f64,0xaa1faf64,0x2a1f2f64,0xaa1faf64,0x2a1f2f64,0xaa1faf64,0x2a1f2f64,0xaa1faf64,0xaf64aa1f,0x2f642a1f,0xaf64aa1f,0x2f642a1f,
0xaa1f2da8,0x2f642da8,0x2a1fada8,0xaf64ada8,0x2f640000,0xaa1fb000,0xaf640000,0x2a1f3000,0xaf64ada8,0xaa1f2da8,0x2f642da8,0x2a1fada8,0x2a1f3000,0x2f648000,0xaa1fb000,0xaf640000,
0xaea7263e,0x2c722fd9,0x2ea7a63e,0xac72afd9,0x2fd92c72,0x263eaea7,0xafd9ac72,0xa63e2ea7,0xac72afd9,0xaea7263e,0x2c722fd9,0x2ea7a63e,0xa63e2ea7,0x2fd92c72,0x263eaea7,0xafd9ac72,
0xada82da8,0xada82da8,0xada82da8,0xada82da8,0x2da8ada8,0x2da8ada8,0x2da8ada8,0x2da8ada8,0x2da82da8,0x2da82da8,0x2da82da8,0x2da82da8,0xada8ada8,0xada8ada8,0xada8ada8,0xada8ada8,
0x3000,0x3000,0x3000,0x80003000,0x8000b000,0x8000b000,0x8000b000,0x8000b000,0x30000000,0x30008000,0x30008000,0x30008000,0xb0000000,0xb0000000,0xb0000000,0xb0000000,
0x2ea7263e,0xac722fd9,0xaea7a63e,0x2c72afd9,0xafd92c72,0xa63eaea7,0x2fd9ac72,0x263e2ea7,0x2c72afd9,0x2ea7263e,0xac722fd9,0xaea7a63e,0x263e2ea7,0xafd92c72,0xa63eaea7,0x2fd9ac72,
0x2f64ada8,0x2a1f2da8,0xaf642da8,0xaa1fada8,0xaa1f3000,0xaf640000,0x2a1fb000,0x2f648000,0xaa1fada8,0x2f64ada8,0x2a1f2da8,0xaf642da8,0x2f640000,0xaa1f3000,0xaf640000,0x2a1fb000,
0xaa1f2f64,0x2a1faf64,0xaa1f2f64,0x2a1faf64,0x2f64aa1f,0xaf642a1f,0x2f64aa1f,0xaf642a1f,0xaf642a1f,0x2f64aa1f,0xaf642a1f,0x2f64aa1f,0xaa1f2f64,0x2a1faf64,0xaa1f2f64,0x2a1faf64,
0x2da80000,0xada80000,0x2da88000,0xada80000,0x2da8b000,0xada83000,0x2da8b000,0xada83000,0xada83000,0x2da8b000,0xada83000,0x2da8b000,0x2da88000,0xada80000,0x2da88000,0xada88000,
0xa63e2c72,0x2fd9aea7,0x263eac72,0xafd92ea7,0xaea72fd9,0x2c72a63e,0x2ea7afd9,0xac72263e,0xafd92ea7,0xa63e2c72,0x2fd9aea7,0x263eac72,0xac72263e,0xaea72fd9,0x2c72a63e,0x2ea7afd9,
0x2f64ada8,0x2a1fada8,0xaf642da8,0xaa1f2da8,0x2a1f0000,0x2f64b000,0xaa1f0000,0xaf643000,0xaa1f2da8,0x2f64ada8,0x2a1fada8,0xaf642da8,0xaf643000,0x2a1f8000,0x2f64b000,0xaa1f8000,
0xb0003000,0xb0003000,0xb0003000,0xb0003000,0xb0003000,0xb0003000,0xb0003000,0xb0003000,0x0,0x8000,0x8000,0x80008000,0x8000,0x8000,0x8000,0x8000,
0x80000000,0x80000000,0x80008000,0x80008000,0x80000000,0x80008000,0x80008000,0x80008000,0xb0003000,0xb0003000,0xb0003000,0xb0003000,0xb0003000,0xb0003000,0xb0003000,0xb0003000,
0xaa1f2da8,0x2f64ada8,0x2a1fada8,0xaf642da8,0xaf643000,0x2a1f0000,0x2f64b000,0xaa1f8000,0xaf642da8,0xaa1f2da8,0x2f64ada8,0x2a1fada8,0xaa1f0000,0xaf643000,0x2a1f0000,0x2f64b000,
0x2fd9aea7,0x263eac72,0xafd92ea7,0xa63e2c72,0x2c72a63e,0x2ea7afd9,0xac72263e,0xaea72fd9,0xa63e2c72,0x2fd9aea7,0x263eac72,0xafd92ea7,0xaea72fd9,0x2c72a63e,0x2ea7afd9,0xac72263e,
0xada80000,0x2da80000,0xada88000,0x2da80000,0xada83000,0x2da8b000,0xada83000,0x2da8b000,0xada83000,0x2da8b000,0xada83000,0x2da8b000,0x2da80000,0xada88000,0x2da88000,0xada88000,
0xaa1f2f64,0x2a1faf64,0xaa1f2f64,0x2a1faf64,0x2f64aa1f,0xaf642a1f,0x2f64aa1f,0xaf642a1f,0x2f64aa1f,0xaf642a1f,0x2f64aa1f,0xaf642a1f,0x2a1faf64,0xaa1f2f64,0x2a1faf64,0xaa1f2f64,
0x2a1f2da8,0xaf642da8,0xaa1fada8,0x2f64ada8,0xaf640000,0x2a1fb000,0x2f640000,0xaa1f3000,0x2f64ada8,0x2a1f2da8,0xaf642da8,0xaa1fada8,0xaa1f3000,0xaf648000,0x2a1fb000,0x2f640000,
0x2c72afd9,0x2ea7263e,0xac722fd9,0xaea7a63e,0x263e2ea7,0xafd92c72,0xa63eaea7,0x2fd9ac72,0xaea7a63e,0x2c72afd9,0x2ea7263e,0xac722fd9,0x2fd9ac72,0x263e2ea7,0xafd92c72,0xa63eaea7,
0x2da8ada8,0x2da8ada8,0x2da8ada8,0x2da8ada8,0xada82da8,0xada82da8,0xada82da8,0xada82da8,0x2da82da8,0x2da82da8,0x2da82da8,0x2da82da8,0xada8ada8,0xada8ada8,0xada8ada8,0xada8ada8,
0x80003000,0x80003000,0x80003000,0x3000,0xb000,0x8000b000,0xb000,0xb000,0xb0000000,0xb0008000,0xb0008000,0xb0008000,0x30000000,0x30000000,0x30000000,0x30008000,
0x2c722fd9,0x2ea7a63e,0xac72afd9,0xaea7263e,0x263eaea7,0xafd9ac72,0xa63e2ea7,0x2fd92c72,0xaea7263e,0x2c722fd9,0x2ea7a63e,0xac72afd9,0x2fd92c72,0x263eaea7,0xafd9ac72,0xa63e2ea7,
0xaf64ada8,0xaa1f2da8,0x2f642da8,0x2a1fada8,0x2a1f3000,0x2f648000,0xaa1fb000,0xaf648000,0x2a1fada8,0xaf64ada8,0xaa1f2da8,0x2f642da8,0xaf640000,0x2a1f3000,0x2f648000,0xaa1fb000,
0x2f642a1f,0xaf64aa1f,0x2f642a1f,0xaf64aa1f,0x2a1f2f64,0xaa1faf64,0x2a1f2f64,0xaa1faf64,0xaa1faf64,0x2a1f2f64,0xaa1faf64,0x2a1f2f64,0x2f642a1f,0xaf64aa1f,0x2f642a1f,0xaf64aa1f,
0xada80000,0x2da80000,0xada88000,0x2da88000,0xada8b000,0x2da83000,0xada8b000,0x2da83000,0x2da83000,0xada8b000,0x2da83000,0xada8b000,0xada88000,0x2da88000,0xada88000,0x2da80000,
0x2fd92ea7,0x263e2c72,0xafd9aea7,0xa63eac72,0x2c72263e,0x2ea72fd9,0xac72a63e,0xaea7afd9,0xa63eac72,0x2fd92ea7,0x263e2c72,0xafd9aea7,0xaea7afd9,0x2c72263e,0x2ea72fd9,0xac72a63e,
0xaf64ada8,0xaa1fada8,0x2f642da8,0x2a1f2da8,0xaa1f0000,0xaf64b000,0x2a1f0000,0x2f643000,0x2a1f2da8,0xaf64ada8,0xaa1fada8,0x2f642da8,0x2f643000,0xaa1f8000,0xaf64b000,0x2a1f0000,
0x80008000,0x80008000,0x80008000,0x80008000,0x80008000,0x80008000,0x80008000,0x80008000,0x30003000,0x30003000,0x30003000,0x30003000,0x30003000,0x30003000,0x30003000,0x30003000,
0x80008000,0x80008000,0x80008000,0x80008000,0x80008000,0x80008000,0x80008000,0x80008000,0x30003000,0x30003000,0x30003000,0x30003000,0x30003000,0x30003000,0x30003000,0x30003000,
0xaf64ada8,0xaa1fada8,0x2f642da8,0x2a1f2da8,0xaa1f8000,0xaf64b000,0x2a1f8000,0x2f643000,0x2a1f2da8,0xaf64ada8,0xaa1fada8,0x2f642da8,0x2f643000,0xaa1f0000,0xaf64b000,0x2a1f8000,
0xafd9aea7,0xa63eac72,0x2fd92ea7,0x263e2c72,0xac72a63e,0xaea7afd9,0x2c72263e,0x2ea72fd9,0x263e2c72,0xafd9aea7,0xa63eac72,0x2fd92ea7,0x2ea72fd9,0xac72a63e,0xaea7afd9,0x2c72263e,
0x2da83000,0xada8b000,0x2da83000,0xada8b000,0xada80000,0x2da88000,0xada80000,0x2da88000,0xada88000,0x2da88000,0xada80000,0x2da88000,0xada8b000,0x2da83000,0xada8b000,0x2da83000,
0x2a1f2f64,0xaa1faf64,0x2a1f2f64,0xaa1faf64,0xaf64aa1f,0x2f642a1f,0xaf64aa1f,0x2f642a1f,0xaf64aa1f,0x2f642a1f,0xaf64aa1f,0x2f642a1f,0xaa1faf64,0x2a1f2f64,0xaa1faf64,0x2a1f2f64,
0xaf64ada8,0xaa1f2da8,0x2f642da8,0x2a1fada8,0x2a1f3000,0x2f648000,0xaa1fb000,0xaf640000,0x2a1fada8,0xaf64ada8,0xaa1f2da8,0x2f642da8,0xaf648000,0x2a1f3000,0x2f648000,0xaa1fb000,
0xac72afd9,0xaea7263e,0x2c722fd9,0x2ea7a63e,0xa63e2ea7,0x2fd92c72,0x263eaea7,0xafd9ac72,0x2ea7a63e,0xac72afd9,0xaea7263e,0x2c722fd9,0xafd9ac72,0xa63e2ea7,0x2fd92c72,0x263eaea7,
0xada8ada8,0xada8ada8,0xada8ada8,0xada8ada8,0x2da82da8,0x2da82da8,0x2da82da8,0x2da82da8,0xada82da8,0xada82da8,0xada82da8,0xada82da8,0x2da8ada8,0x2da8ada8,0x2da8ada8,0x2da8ada8,
0xb0008000,0xb0000000,0xb0000000,0xb0000000,0x30008000,0x30008000,0x30008000,0x30008000,0x3000,0x3000,0x3000,0x80003000,0x8000b000,0x8000b000,0x8000b000,0x8000b000,
0xac722fd9,0xaea7a63e,0x2c72afd9,0x2ea7263e,0xa63eaea7,0x2fd9ac72,0x263e2ea7,0xafd92c72,0x2ea7263e,0xac722fd9,0xaea7a63e,0x2c72afd9,0xafd92c72,0xa63eaea7,0x2fd9ac72,0x263e2ea7,
0x2a1f2da8,0xaf642da8,0xaa1fada8,0x2f64ada8,0xaf648000,0x2a1fb000,0x2f648000,0xaa1f3000,0x2f64ada8,0x2a1f2da8,0xaf642da8,0xaa1fada8,0xaa1f3000,0xaf640000,0x2a1fb000,0x2f648000,
0xaf642a1f,0x2f64aa1f,0xaf642a1f,0x2f64aa1f,0xaa1f2f64,0x2a1faf64,0xaa1f2f64,0x2a1faf64,0x2a1faf64,0xaa1f2f64,0x2a1faf64,0xaa1f2f64,0xaf642a1f,0x2f64aa1f,0xaf642a1f,0x2f64aa1f,
0xada83000,0x2da8b000,0xada83000,0x2da8b000,0x2da88000,0xada80000,0x2da88000,0xada88000,0xada88000,0x2da88000,0xada80000,0x2da88000,0xada83000,0x2da8b000,0xada83000,0x2da8b000,
0xafd92ea7,0xa63e2c72,0x2fd9aea7,0x263eac72,0xac72263e,0xaea72fd9,0x2c72a63e,0x2ea7afd9,0x263eac72,0xafd92ea7,0xa63e2c72,0x2fd9aea7,0x2ea7afd9,0xac72263e,0xaea72fd9,0x2c72a63e,
0xaa1f2da8,0x2f64ada8,0x2a1fada8,0xaf642da8,0xaf643000,0x2a1f8000,0x2f64b000,0xaa1f8000,0xaf642da8,0xaa1f2da8,0x2f64ada8,0x2a1fada8,0xaa1f8000,0xaf643000,0x2a1f8000,0x2f64b000,
0x80008000,0x80000000,0x80000000,0x0,0x80000000,0x80000000,0x80000000,0x80000000,0xb0003000,0xb0003000,0xb0003000,0xb0003000,0xb0003000,0xb0003000,0xb0003000,0xb0003000,
0x3000b000,0x3000b000,0x3000b000,0x3000b000,0x3000b000,0x3000b000,0x3000b000,0x3000b000,0x80000000,0x80000000,0x80008000,0x80008000,0x80000000,0x80008000,0x80008000,0x80008000,
0x2f64ada8,0x2a1fada8,0xaf642da8,0xaa1f2da8,0x2a1f8000,0x2f64b000,0xaa1f8000,0xaf643000,0xaa1f2da8,0x2f64ada8,0x2a1fada8,0xaf642da8,0xaf643000,0x2a1f0000,0x2f64b000,0xaa1f8000,
0x263eac72,0xafd92ea7,0xa63e2c72,0x2fd9aea7,0x2ea7afd9,0xac72263e,0xaea72fd9,0x2c72a63e,0x2fd9aea7,0x263eac72,0xafd92ea7,0xa63e2c72,0x2c72a63e,0x2ea7afd9,0xac72263e,0xaea72fd9,
0xada83000,0x2da8b000,0xada83000,0x2da8b000,0x2da80000,0xada88000,0x2da88000,0xada88000,0x2da88000,0xada88000,0x2da80000,0xada88000,0x2da8b000,0xada83000,0x2da8b000,0xada83000,
0x2f64aa1f,0xaf642a1f,0x2f64aa1f,0xaf642a1f,0x2a1faf64,0xaa1f2f64,0x2a1faf64,0xaa1f2f64,0x2a1faf64,0xaa1f2f64,0x2a1faf64,0xaa1f2f64,0xaf642a1f,0x2f64aa1f,0xaf642a1f,0x2f64aa1f,
0x2f64ada8,0x2a1f2da8,0xaf642da8,0xaa1fada8,0xaa1f3000,0xaf648000,0x2a1fb000,0x2f640000,0xaa1fada8,0x2f64ada8,0x2a1f2da8,0xaf642da8,0x2f648000,0xaa1f3000,0xaf648000,0x2a1fb000,
0xaea7a63e,0x2c72afd9,0x2ea7263e,0xac722fd9,0x2fd9ac72,0x263e2ea7,0xafd92c72,0xa63eaea7,0xac722fd9,0xaea7a63e,0x2c72afd9,0x2ea7263e,0xa63eaea7,0x2fd9ac72,0x263e2ea7,0xafd92c72,
0xada8ada8,0xada8ada8,0xada8ada8,0xada8ada8,0x2da82da8,0x2da82da8,0x2da82da8,0x2da82da8,0x2da8ada8,0x2da8ada8,0x2da8ada8,0x2da8ada8,0xada82da8,0xada82da8,0xada82da8,0xada82da8,
0x30008000,0x30000000,0x30000000,0x30000000,0xb0008000,0xb0008000,0xb0008000,0xb0000000,0x80003000,0x80003000,0x80003000,0x3000,0xb000,0x8000b000,0xb000,0xb000,
0x2ea7a63e,0xac72afd9,0xaea7263e,0x2c722fd9,0xafd9ac72,0xa63e2ea7,0x2fd92c72,0x263eaea7,0x2c722fd9,0x2ea7a63e,0xac72afd9,0xaea7263e,0x263eaea7,0xafd9ac72,0xa63e2ea7,0x2fd92c72,
0xaa1f2da8,0x2f642da8,0x2a1fada8,0xaf64ada8,0x2f648000,0xaa1fb000,0xaf640000,0x2a1f3000,0xaf64ada8,0xaa1f2da8,0x2f642da8,0x2a1fada8,0x2a1f3000,0x2f648000,0xaa1fb000,0xaf648000,
0xaa1faf64,0x2a1f2f64,0xaa1faf64,0x2a1f2f64,0x2f642a1f,0xaf64aa1f,0x2f642a1f,0xaf64aa1f,0xaf64aa1f,0x2f642a1f,0xaf64aa1f,0x2f642a1f,0xaa1faf64,0x2a1f2f64,0xaa1faf64,0x2a1f2f64,
0x2da83000,0xada8b000,0x2da83000,0xada8b000,0xada88000,0x2da88000,0xada88000,0x2da80000,0x2da88000,0xada88000,0x2da80000,0xada80000,0x2da83000,0xada8b000,0x2da83000,0xada8b000,
0xa63eac72,0x2fd92ea7,0x263e2c72,0xafd9aea7,0xaea7afd9,0x2c72263e,0x2ea72fd9,0xac72a63e,0xafd9aea7,0xa63eac72,0x2fd92ea7,0x263e2c72,0xac72a63e,0xaea7afd9,0x2c72263e,0x2ea72fd9,
0x2a1f2da8,0xaf64ada8,0xaa1fada8,0x2f642da8,0x2f643000,0xaa1f8000,0xaf64b000,0x2a1f0000,0x2f642da8,0x2a1f2da8,0xaf64ada8,0xaa1fada8,0x2a1f8000,0x2f643000,0xaa1f8000,0xaf64b000,
0x3c003c00,0x3c003c00,0x3c003c00,0x3c003c00,0x3c003c00,0x3c003c00,0x3c003c00,0x3c003c00,0x80008000,0x80008000,0x80008000,0x80008000,0x80008000,0x80008000,0x80008000,0x80008000,
0x3bd93c00,0x3aa73b64,0x387239a8,0x323e361f,0xb23e0000,0xb872b61f,0xbaa7b9a8,0xbbd9bb64,0xb23e8000,0xb872b61f,0xbaa7b9a8,0xbbd9bb64,0xbbd9bc00,0xbaa7bb64,0xb872b9a8,0xb23eb61f,
0xbb64bc00,0xb61fb9a8,0x361f8000,0x3b6439a8,0x3b643c00,0x361f39a8,0xb61f0000,0xbb64b9a8,0x361f8000,0x3b6439a8,0x3b643c00,0x361f39a8,0xb61f8000,0xbb64b9a8,0xbb64bc00,0xb61fb9a8,
0x38728000,0x3bd93b64,0x323e39a8,0xbaa7b61f,0x3aa73c00,0xb23e361f,0xbbd9b9a8,0xb872bb64,0x3aa73c00,0xb23e361f,0xbbd9b9a8,0xb872bb64,0xb8728000,0xbbd9bb64,0xb23eb9a8,0x3aa7361f,
0xbc008000,0x3c008000,0xbc000000,0x3c008000,0xbc000000,0x3c008000,0xbc000000,0x3c008000,0x3c00,0x8000bc00,0x3c00,0x8000bc00,0x3c00,0x8000bc00,0x80003c00,0x8000bc00,
0xbbd98000,0x3aa7361f,0xb872b9a8,0x323e3b64,0x323ebc00,0xb8723b64,0x3aa7b9a8,0xbbd9361f,0xb23e3c00,0x3872bb64,0xbaa739a8,0x3bd9b61f,0xbbd90000,0x3aa7361f,0xb872b9a8,0x323e3b64,
0x3b648000,0xb61fb9a8,0xb61f3c00,0x3b64b9a8,0xbb648000,0x361f39a8,0x361fbc00,0xbb6439a8,0x361fbc00,0xbb6439a8,0x3b648000,0xb61fb9a8,0xb61f3c00,0x3b64b9a8,0xbb640000,0x361f39a8,
0xb8723c00,0x3bd9b61f,0xb23eb9a8,0xbaa73b64,0xbaa78000,0xb23e3b64,0x3bd9b9a8,0xb872b61f,0x3aa78000,0x323ebb64,0xbbd939a8,0x3872361f,0xb8723c00,0x3bd9b61f,0xb23eb9a8,0xbaa73b64,
0xbbd93c00,0xbaa73b64,0xb87239a8,0xb23e361f,0x323e8000,0x3872b61f,0x3aa7b9a8,0x3bd9bb64,0x323e8000,0x3872b61f,0x3aa7b9a8,0x3bd9bb64,0x3bd9bc00,0x3aa7bb64,0x3872b9a8,0x323eb61f,
0xbc003c00,0xbc003c00,0xbc003c00,0xbc003c00,0xbc003c00,0xbc003c00,0xbc003c00,0xbc003c00,0x80008000,0x80000000,0x80000000,0x80000000,0x80000000,0x80000000,0x0,0x80000000,
0xb8728000,0xbbd93b64,0xb23e39a8,0x3aa7b61f,0xbaa73c00,0x323e361f,0x3bd9b9a8,0x3872bb64,0xbaa73c00,0x323e361f,0x3bd9b9a8,0x3872bb64,0x38728000,0x3bd9bb64,0x323eb9a8,0xbaa7361f,
0x3b64bc00,0x361fb9a8,0xb61f8000,0xbb6439a8,0xbb643c00,0xb61f39a8,0x361f0000,0x3b64b9a8,0xb61f8000,0xbb6439a8,0xbb643c00,0xb61f39a8,0x361f8000,0x3b64b9a8,0x3b64bc00,0x361fb9a8,
0x3bd98000,0xbaa7361f,0x3872b9a8,0xb23e3b64,0xb23ebc00,0x38723b64,0xbaa7b9a8,0x3bd9361f,0x323e3c00,0xb872bb64,0x3aa739a8,0xbbd9b61f,0x3bd98000,0xbaa7361f,0x3872b9a8,0xb23e3b64,
0x3c008000,0xbc008000,0x3c000000,0xbc008000,0x3c000000,0xbc008000,0x3c000000,0xbc000000,0x80003c00,0xbc00,0x80003c00,0x8000bc00,0x80003c00,0xbc00,0x80003c00,0xbc00,
0x38723c00,0xbbd9b61f,0x323eb9a8,0x3aa73b64,0x3aa78000,0x323e3b64,0xbbd9b9a8,0x3872b61f,0xbaa78000,0xb23ebb64,0x3bd939a8,0xb872361f,0x38723c00,0xbbd9b61f,0x323eb9a8,0x3aa73b64,
0xbb640000,0x361fb9a8,0x361f3c00,0xbb64b9a8,0x3b648000,0xb61f39a8,0xb61fbc00,0x3b6439a8,0xb61fbc00,0x3b6439a8,0xbb640000,0x361fb9a8,0x361f3c00,0xbb64b9a8,0x3b648000,0xb61f39a8,
0x39a83c00,0xb9a80000,0xb9a8bc00,0x39a88000,0x39a83c00,0xb9a80000,0xb9a8bc00,0x39a88000,0xb9a88000,0xb9a8bc00,0x39a88000,0x39a83c00,0xb9a80000,0xb9a8bc00,0x39a88000,0x39a83c00,
0x38723c00,0xbbd9b61f,0x323eb9a8,0x3aa73b64,0xbaa70000,0xb23ebb64,0x3bd939a8,0xb872361f,0xbaa78000,0xb23ebb64,0x3bd939a8,0xb872361f,0xb872bc00,0x3bd9361f,0xb23e39a8,0xbaa7bb64,
0xb61fbc00,0x3b6439a8,0xbb640000,0x361fb9a8,0x361f3c00,0xbb64b9a8,0x3b648000,0xb61f39a8,0x3b648000,0xb61f39a8,0xb61fbc00,0x3b6439a8,0xbb648000,0x361fb9a8,0x361f3c00,0xbb64b9a8,
0x3bd98000,0xbaa7361f,0x3872b9a8,0xb23e3b64,0x323e3c00,0xb872bb64,0x3aa739a8,0xbbd9b61f,0x323e3c00,0xb872bb64,0x3aa739a8,0xbbd9b61f,0xbbd98000,0x3aa7b61f,0xb87239a8,0x323ebb64,
0xb9a88000,0xb9a83c00,0x39a88000,0x39a8bc00,0xb9a80000,0xb9a83c00,0x39a88000,0x39a8bc00,0xb9a83c00,0x39a88000,0x39a8bc00,0xb9a80000,0xb9a83c00,0x39a88000,0x39a8bc00,0xb9a88000,
0xb8728000,0xbbd93b64,0xb23e39a8,0x3aa7b61f,0x3aa7bc00,0xb23eb61f,0xbbd939a8,0xb8723b64,0xbaa73c00,0x323e361f,0x3bd9b9a8,0x3872bb64,0xb8728000,0xbbd93b64,0xb23e39a8,0x3aa7b61f,
0x361f8000,0x3b64b9a8,0x3b64bc00,0x361fb9a8,0xb61f8000,0xbb6439a8,0xbb643c00,0xb61f39a8,0x3b64bc00,0x361fb9a8,0xb61f8000,0xbb6439a8,0xbb643c00,0xb61f39a8,0x361f8000,0x3b64b9a8,
0xbbd93c00,0xbaa73b64,0xb87239a8,0xb23e361f,0xb23e8000,0xb872361f,0xbaa739a8,0xbbd93b64,0x323e8000,0x3872b61f,0x3aa7b9a8,0x3bd9bb64,0xbbd93c00,0xbaa73b64,0xb87239a8,0xb23e361f,
0xb8723c00,0x3bd9b61f,0xb23eb9a8,0xbaa73b64,0x3aa78000,0x323ebb64,0xbbd939a8,0x3872361f,0x3aa78000,0x323ebb64,0xbbd939a8,0x3872361f,0x3872bc00,0xbbd9361f,0x323e39a8,0x3aa7bb64,
0xb9a83c00,0x39a80000,0x39a8bc00,0xb9a88000,0xb9a83c00,0x39a88000,0x39a8bc00,0xb9a88000,0x39a88000,0x39a8bc00,0xb9a88000,0xb9a83c00,0x39a80000,0x39a8bc00,0xb9a88000,0xb9a83c00,
0xbbd98000,0x3aa7361f,0xb872b9a8,0x323e3b64,0xb23e3c00,0x3872bb64,0xbaa739a8,0x3bd9b61f,0xb23e3c00,0x3872bb64,0xbaa739a8,0x3bd9b61f,0x3bd98000,0xbaa7b61f,0x387239a8,0xb23ebb64,
0x361fbc00,0xbb6439a8,0x3b640000,0xb61fb9a8,0xb61f3c00,0x3b64b9a8,0xbb648000,0x361f39a8,0xbb648000,0x361f39a8,0x361fbc00,0xbb6439a8,0x3b648000,0xb61fb9a8,0xb61f3c00,0x3b64b9a8,
0x38728000,0x3bd93b64,0x323e39a8,0xbaa7b61f,0xbaa7bc00,0x323eb61f,0x3bd939a8,0x38723b64,0x3aa73c00,0xb23e361f,0xbbd9b9a8,0xb872bb64,0x38728000,0x3bd93b64,0x323e39a8,0xbaa7b61f,
0x39a88000,0x39a83c00,0xb9a88000,0xb9a8bc00,0x39a80000,0x39a83c00,0xb9a80000,0xb9a8bc00,0x39a83c00,0xb9a88000,0xb9a8bc00,0x39a88000,0x39a83c00,0xb9a88000,0xb9a8bc00,0x39a80000,
0x3bd93c00,0x3aa73b64,0x387239a8,0x323e361f,0x323e8000,0x3872361f,0x3aa739a8,0x3bd93b64,0xb23e8000,0xb872b61f,0xbaa7b9a8,0xbbd9bb64,0x3bd93c00,0x3aa73b64,0x387239a8,0x323e361f,
0xb61f8000,0xbb64b9a8,0xbb64bc00,0xb61fb9a8,0x361f8000,0x3b6439a8,0x3b643c00,0x361f39a8,0xbb64bc00,0xb61fb9a8,0x361f0000,0x3b6439a8,0x3b643c00,0x361f39a8,0xb61f8000,0xbb64b9a8,
0x0,0x0,0x0,0x0,0x0,0x0,0x0,0x0,0x3c003c00,0x3c003c00,0x3c003c00,0x3c003c00,0x3c003c00,0x3c003c00,0x3c003c00,0x3c003c00,
0x323e0000,0x3872361f,0x3aa739a8,0x3bd93b64,0x3bd93c00,0x3aa73b64,0x387239a8,0x323e361f,0x3bd93c00,0x3aa73b64,0x387239a8,0x323e361f,0xb23e0000,0xb872b61f,0xbaa7b9a8,0xbbd9bb64,
0xb61f0000,0xbb64b9a8,0xbb64bc00,0xb61fb9a8,0x361f0000,0x3b6439a8,0x3b643c00,0x361f39a8,0xbb64bc00,0xb61fb9a8,0x361f8000,0x3b6439a8,0x3b643c00,0x361f39a8,0xb61f0000,0xbb64b9a8,
0xbaa7bc00,0x323eb61f,0x3bd939a8,0x38723b64,0x38720000,0x3bd93b64,0x323e39a8,0xbaa7b61f,0x38728000,0x3bd93b64,0x323e39a8,0xbaa7b61f,0x3aa73c00,0xb23e361f,0xbbd9b9a8,0xb872bb64,
0x3c00,0x8000bc00,0x3c00,0x8000bc00,0x3c00,0x8000bc00,0x80003c00,0x8000bc00,0x3c000000,0xbc000000,0x3c008000,0xbc000000,0x3c008000,0xbc000000,0x3c008000,0xbc000000,
0xb23e3c00,0x3872bb64,0xbaa739a8,0x3bd9b61f,0xbbd90000,0x3aa7361f,0xb872b9a8,0x323e3b64,0x3bd90000,0xbaa7b61f,0x387239a8,0xb23ebb64,0xb23e3c00,0x3872bb64,0xbaa739a8,0x3bd9b61f,
0x361fbc00,0xbb6439a8,0x3b648000,0xb61fb9a8,0xb61f3c00,0x3b64b9a8,0xbb640000,0x361f39a8,0xbb640000,0x361f39a8,0x361fbc00,0xbb6439a8,0x3b640000,0xb61fb9a8,0xb61f3c00,0x3b64b9a8,
0x3aa78000,0x323ebb64,0xbbd939a8,0x3872361f,0xb8723c00,0x3bd9b61f,0xb23eb9a8,0xbaa73b64,0x3872bc00,0xbbd9361f,0x323e39a8,0x3aa7bb64,0x3aa70000,0x323ebb64,0xbbd939a8,0x3872361f,
0xb23e0000,0xb872361f,0xbaa739a8,0xbbd93b64,0xbbd93c00,0xbaa73b64,0xb87239a8,0xb23e361f,0xbbd93c00,0xbaa73b64,0xb87239a8,0xb23e361f,0x323e8000,0x3872b61f,0x3aa7b9a8,0x3bd9bb64,
0x0,0x8000,0x8000,0x8000,0x8000,0x8000,0x80008000,0x8000,0xbc003c00,0xbc003c00,0xbc003c00,0xbc003c00,0xbc003c00,0xbc003c00,0xbc003c00,0xbc003c00,
0x3aa7bc00,0xb23eb61f,0xbbd939a8,0xb8723b64,0xb8720000,0xbbd93b64,0xb23e39a8,0x3aa7b61f,0xb8728000,0xbbd93b64,0xb23e39a8,0x3aa7b61f,0xbaa73c00,0x323e361f,0x3bd9b9a8,0x3872bb64,
0x361f0000,0x3b64b9a8,0x3b64bc00,0x361fb9a8,0xb61f0000,0xbb6439a8,0xbb643c00,0xb61f39a8,0x3b64bc00,0x361fb9a8,0xb61f8000,0xbb6439a8,0xbb643c00,0xb61f39a8,0x361f0000,0x3b64b9a8,
0x323e3c00,0xb872bb64,0x3aa739a8,0xbbd9b61f,0x3bd98000,0xbaa7361f,0x3872b9a8,0xb23e3b64,0xbbd90000,0x3aa7b61f,0xb87239a8,0x323ebb64,0x323e3c00,0xb872bb64,0x3aa739a8,0xbbd9b61f,
0x80003c00,0xbc00,0x80003c00,0x8000bc00,0x80003c00,0xbc00,0x80003c00,0xbc00,0xbc000000,0x3c000000,0xbc008000,0x3c000000,0xbc008000,0x3c000000,0xbc008000,0x3c008000,
0xbaa78000,0xb23ebb64,0x3bd939a8,0xb872361f,0x38723c00,0xbbd9b61f,0x323eb9a8,0x3aa73b64,0xb872bc00,0x3bd9361f,0xb23e39a8,0xbaa7bb64,0xbaa70000,0xb23ebb64,0x3bd939a8,0xb872361f,
0xb61fbc00,0x3b6439a8,0xbb640000,0x361fb9a8,0x361f3c00,0xbb64b9a8,0x3b648000,0xb61f39a8,0x3b648000,0xb61f39a8,0xb61fbc00,0x3b6439a8,0xbb640000,0x361fb9a8,0x361f3c00,0xbb64b9a8,
0x39a80000,0x39a83c00,0xb9a80000,0xb9a8bc00,0x39a88000,0x39a83c00,0xb9a80000,0xb9a8bc00,0x39a83c00,0xb9a80000,0xb9a8bc00,0x39a88000,0x39a83c00,0xb9a80000,0xb9a8bc00,0x39a88000,
0x3aa70000,0x323e3b64,0xbbd9b9a8,0x3872b61f,0x38723c00,0xbbd9b61f,0x323eb9a8,0x3aa73b64,0x38723c00,0xbbd9b61f,0x323eb9a8,0x3aa73b64,0xbaa70000,0xb23ebb64,0x3bd939a8,0xb872361f,
0xbb640000,0x361fb9a8,0x361f3c00,0xbb64b9a8,0x3b640000,0xb61f39a8,0xb61fbc00,0x3b6439a8,0xb61fbc00,0x3b6439a8,0xbb640000,0x361fb9a8,0x361f3c00,0xbb64b9a8,0x3b648000,0xb61f39a8,
0xb23ebc00,0x38723b64,0xbaa7b9a8,0x3bd9361f,0x3bd90000,0xbaa7361f,0x3872b9a8,0xb23e3b64,0x3bd98000,0xbaa7361f,0x3872b9a8,0xb23e3b64,0x323e3c00,0xb872bb64,0x3aa739a8,0xbbd9b61f,
0xb9a83c00,0x39a88000,0x39a8bc00,0xb9a80000,0xb9a83c00,0x39a88000,0x39a8bc00,0xb9a88000,0x39a80000,0x39a8bc00,0xb9a80000,0xb9a83c00,0x39a88000,0x39a8bc00,0xb9a80000,0xb9a83c00,
0xbaa73c00,0x323e361f,0x3bd9b9a8,0x3872bb64,0xb8728000,0xbbd93b64,0xb23e39a8,0x3aa7b61f,0x38720000,0x3bd9bb64,0x323eb9a8,0xbaa7361f,0xbaa73c00,0x323e361f,0x3bd9b9a8,0x3872bb64,
0x3b64bc00,0x361fb9a8,0xb61f8000,0xbb6439a8,0xbb643c00,0xb61f39a8,0x361f8000,0x3b64b9a8,0xb61f0000,0xbb6439a8,0xbb643c00,0xb61f39a8,0x361f0000,0x3b64b9a8,0x3b64bc00,0x361fb9a8,
0x323e8000,0x3872b61f,0x3aa7b9a8,0x3bd9bb64,0xbbd93c00,0xbaa73b64,0xb87239a8,0xb23e361f,0x3bd9bc00,0x3aa7bb64,0x3872b9a8,0x323eb61f,0x323e0000,0x3872b61f,0x3aa7b9a8,0x3bd9bb64,
0xbaa70000,0xb23e3b64,0x3bd9b9a8,0xb872b61f,0xb8723c00,0x3bd9b61f,0xb23eb9a8,0xbaa73b64,0xb8723c00,0x3bd9b61f,0xb23eb9a8,0xbaa73b64,0x3aa78000,0x323ebb64,0xbbd939a8,0x3872361f,
0xb9a80000,0xb9a83c00,0x39a80000,0x39a8bc00,0xb9a88000,0xb9a83c00,0x39a80000,0x39a8bc00,0xb9a83c00,0x39a80000,0x39a8bc00,0xb9a88000,0xb9a83c00,0x39a88000,0x39a8bc00,0xb9a88000,
0x323ebc00,0xb8723b64,0x3aa7b9a8,0xbbd9361f,0xbbd90000,0x3aa7361f,0xb872b9a8,0x323e3b64,0xbbd98000,0x3aa7361f,0xb872b9a8,0x323e3b64,0xb23e3c00,0x3872bb64,0xbaa739a8,0x3bd9b61f,
0x3b640000,0xb61fb9a8,0xb61f3c00,0x3b64b9a8,0xbb640000,0x361f39a8,0x361fbc00,0xbb6439a8,0x361fbc00,0xbb6439a8,0x3b640000,0xb61fb9a8,0xb61f3c00,0x3b64b9a8,0xbb648000,0x361f39a8,
0x3aa73c00,0xb23e361f,0xbbd9b9a8,0xb872bb64,0x38728000,0x3bd93b64,0x323e39a8,0xbaa7b61f,0xb8720000,0xbbd9bb64,0xb23eb9a8,0x3aa7361f,0x3aa73c00,0xb23e361f,0xbbd9b9a8,0xb872bb64,
0x39a83c00,0xb9a88000,0xb9a8bc00,0x39a88000,0x39a83c00,0xb9a88000,0xb9a8bc00,0x39a80000,0xb9a80000,0xb9a8bc00,0x39a80000,0x39a83c00,0xb9a88000,0xb9a8bc00,0x39a88000,0x39a83c00,
0xb23e8000,0xb872b61f,0xbaa7b9a8,0xbbd9bb64,0x3bd93c00,0x3aa73b64,0x387239a8,0x323e361f,0xbbd9bc00,0xbaa7bb64,0xb872b9a8,0xb23eb61f,0xb23e0000,0xb872b61f,0xbaa7b9a8,0xbbd9bb64,
0xbb64bc00,0xb61fb9a8,0x361f0000,0x3b6439a8,0x3b643c00,0x361f39a8,0xb61f8000,0xbb64b9a8,0x361f0000,0x3b6439a8,0x3b643c00,0x361f39a8,0xb61f0000,0xbb64b9a8,0xbb64bc00,0xb61fb9a8,
};
__device__ __align__(1024) bf16 g_x1T[DM * XP];
__device__ __align__(1024) bf16 g_x2T[DM * XP];
constexpr int FP = SEQ + 32;
__device__ __align__(1024) uint32_t g_fin[DM / 2][FP];
__device__ __align__(1024) float g_sums[2][2][SEQ];

#define TS_DECL
#define TS_ARG
#define TS_PASS
#define TS_PHASE(p)
#define TS(i)
#define TSX(row, i)
#define TS_BEGIN
#define TS_END

__device__ __align__(1024) uint32_t g_keo[DM / 2][2048];
__device__ __align__(128) uint32_t g_ksc[DM];

struct cplx { float r, i; };
__device__ __forceinline__ cplx cmul(cplx a, cplx b) {
    cplx o;
    o.r = fmaf(a.r, b.r, -a.i * b.i);
    o.i = fmaf(a.r, b.i, a.i * b.r);
    return o;
}
__device__ __forceinline__ cplx csq(cplx a) {
    cplx o;
    o.r = fmaf(a.r, a.r, -a.i * a.i);
    o.i = 2.f * a.r * a.i;
    return o;
}
__device__ __forceinline__ cplx cexp_p(float arl, float ai, float p) {
    float mag = ex2(arl * p);
    float ang = ai * p;
    float n = rintf(ang * 0.15915494309189535f);
    float r = fmaf(n, -6.2831854820251465f, ang);
    r = fmaf(n, 1.7484555e-7f, r);
    cplx o;
    o.r = mag * __cosf(r);
    o.i = mag * __sinf(r);
    return o;
}

__device__ __forceinline__ uint32_t pack2h(float lo, float hi) {
    uint32_t r;
    asm("cvt.rn.f16x2.f32 %0, %1, %2;" : "=r"(r) : "f"(hi), "f"(lo));
    return r;
}
__device__ __forceinline__ uint32_t hmul(uint32_t a, uint32_t b) { uint32_t d; asm("mul.rn.f16x2 %0, %1, %2;" : "=r"(d) : "r"(a), "r"(b)); return d; }
__device__ __forceinline__ uint32_t hfma(uint32_t a, uint32_t b, uint32_t c) { uint32_t d; asm("fma.rn.f16x2 %0, %1, %2, %3;" : "=r"(d) : "r"(a), "r"(b), "r"(c)); return d; }
__device__ __forceinline__ uint32_t hfms(uint32_t a, uint32_t b, uint32_t c) {
    uint32_t d;
    asm("{\n.reg .b32 n;\nneg.f16x2 n, %1;\nfma.rn.f16x2 %0, n, %2, %3;\n}" : "=r"(d) : "r"(a), "r"(b), "r"(c));
    return d;
}
__device__ __forceinline__ uint32_t hadd(uint32_t a, uint32_t b) { uint32_t d; asm("add.rn.f16x2 %0, %1, %2;" : "=r"(d) : "r"(a), "r"(b)); return d; }
__device__ __forceinline__ uint32_t hsub(uint32_t a, uint32_t b) { uint32_t d; asm("sub.rn.f16x2 %0, %1, %2;" : "=r"(d) : "r"(a), "r"(b)); return d; }
__device__ __forceinline__ uint4 ldg_tab(int tab, int t) {
    uint4 v;
    asm volatile("ld.global.nc.v4.u32 {%0,%1,%2,%3}, [%4];" : "=r"(v.x), "=r"(v.y), "=r"(v.z), "=r"(v.w) : "l"((const uint4*)c_fft + tab * 128 + t));
    return v;
}
__device__ __forceinline__ uint32_t u4(const uint4& v, int i) { return i == 0 ? v.x : i == 1 ? v.y : i == 2 ? v.z : v.w; }
struct cpair { uint32_t r, i; };
__device__ __forceinline__ cpair pmul(cpair p, uint32_t z) {
    const __half2 zv = *reinterpret_cast<const __half2*>(&z), pr = *reinterpret_cast<const __half2*>(&p.r), pi = *reinterpret_cast<const __half2*>(&p.i);
    const __half2 zr = __low2half2(zv), zi = __high2half2(zv);
    const __half2 a = __hfma2(__hneg2(pi), zi, __hmul2(pr, zr)), b = __hfma2(pi, zr, __hmul2(pr, zi));
    return {*reinterpret_cast<const uint32_t*>(&a), *reinterpret_cast<const uint32_t*>(&b)};
}
__device__ __forceinline__ uint32_t packz(cplx z) { return pack2h(z.r, z.i); }
__device__ __forceinline__ void wgmma_kg(float (&d)[24], uint64_t da, uint64_t db, int scale_d) {
    asm volatile("{\n.reg .pred p;\nsetp.ne.b32 p, %26, 0;\n"
                 "wgmma.mma_async.sync.aligned.m64n48k16.f32.f16.f16 "
                 "{%0,%1,%2,%3,%4,%5,%6,%7,%8,%9,%10,%11,%12,%13,%14,%15,%16,%17,%18,%19,%20,%21,%22,%23}, %24, %25, p, 1, 1, 1, 1;\n}\n"
                 : "+f"(d[0]), "+f"(d[1]), "+f"(d[2]), "+f"(d[3]), "+f"(d[4]), "+f"(d[5]), "+f"(d[6]), "+f"(d[7]), "+f"(d[8]), "+f"(d[9]),
                   "+f"(d[10]), "+f"(d[11]), "+f"(d[12]), "+f"(d[13]), "+f"(d[14]), "+f"(d[15]), "+f"(d[16]), "+f"(d[17]), "+f"(d[18]), "+f"(d[19]),
                   "+f"(d[20]), "+f"(d[21]), "+f"(d[22]), "+f"(d[23])
                 : "l"(da), "l"(db), "r"(scale_d));
}

struct SsmParams { const bf16 *lar, *aim, *cre, *cim, *logdt, *dskip; };
constexpr int KG_TABLES = 6 * 16384, KG_IDX = 6 * 3072, KG_DUMP = KG_IDX + 4096;
struct KgShared { uint32_t kmax[5]; };
struct KgParams { uint32_t l[3], a[3], r[3], i[3], dt, ds; };

__device__ __forceinline__ void kgen_load(KgParams& kp, int d0, int warp, int lane, const SsmParams& sp) {
    const int d = d0 + (warp < 8 ? 2 * (warp >> 2) + (warp & 1) : 4), idx = d * (NMODE / 2) + lane;
    const bf16 *pr = (warp & 2) ? sp.cre : sp.lar, *pi = (warp & 2) ? sp.cim : sp.aim;
#pragma unroll
    for (int j = 0; j < 3; j++) {
        kp.l[j] = __ldg((const uint32_t*)sp.lar + idx + 32 * j); kp.a[j] = __ldg((const uint32_t*)sp.aim + idx + 32 * j);
        kp.r[j] = __ldg((const uint32_t*)pr + idx + 32 * j); kp.i[j] = __ldg((const uint32_t*)pi + idx + 32 * j);
    }
    kp.dt = __ldg((const uint16_t*)sp.logdt + d);
    kp.ds = __ldg((const uint16_t*)sp.dskip + d0 + min(warp >> 1, 4));
}

struct KgAnchors { uint32_t v[8]; };
__device__ __forceinline__ KgAnchors kg_anchor_lo(const KgParams& kp, uint32_t sel, float dt) {
    auto B = [&](uint32_t v) { return __uint_as_float(__byte_perm(v, 0u, sel)); };
    const float arl = -rbf(ex2(B(kp.l[0]) * 1.4426950408889634f)) * dt * 1.4426950408889634f, ai = B(kp.a[0]) * dt;
    const cplx z8 = cexp_p(arl, ai, 8.f), z16 = csq(z8), z24 = cmul(z16, z8), z32 = csq(z16), z64 = csq(z32), z128 = csq(z64), z192 = cmul(z128, z64);
    return {{pack2h(1.f, z8.r), pack2h(0.f, z8.i), pack2h(z16.r, z24.r), pack2h(z16.i, z24.i), packz(z32), packz(z64), packz(z128), packz(z192)}};
}
__device__ __forceinline__ KgAnchors kg_anchor_hi(const KgParams& kp, uint32_t sel, float dt, float cs) {
    auto B = [&](uint32_t v) { return __uint_as_float(__byte_perm(v, 0u, sel)); };
    const float arl = -rbf(ex2(B(kp.l[0]) * 1.4426950408889634f)) * dt * 1.4426950408889634f, ai = B(kp.a[0]) * dt;
    const cplx z1 = cexp_p(arl, -ai, 1.f), z2 = csq(z1), z4 = csq(z2), z256 = cexp_p(arl, -ai, 256.f), z512 = csq(z256), z1024 = csq(z512);
    const cplx H0 = {B(kp.r[0]) * cs, -B(kp.i[0]) * cs}, H4 = cmul(H0, z4);
    return {{pack2h(H0.r, H4.r), pack2h(H0.i, H4.i), packz(z1), packz(z2), packz(z256), packz(z512), packz(z1024), 0u}};
}

template <class Hook>
__device__ __forceinline__ void kgen_tables(KgParams& kp, uint32_t scr, uint32_t dump, int warp, int lane, Hook hook TS_ARG) {
    const int wg = warp >> 2, half = warp & 1, sw = lane & 7;
    const bool hi = warp & 2;
    TS(23);
    const float dt = rbf(ex2(bf_lo(kp.dt) * 1.4426950408889634f));
    uint32_t sel = (wg == 2 && half) ? 0x3244u : 0x1044u;
    float cs = 0.f;
    KgAnchors an;
    if (hi) {
        uint32_t m = 0;
#pragma unroll
        for (int j = 0; j < 3; j++) m = __vmaxu2(m, __vmaxu2(kp.r[j] & 0x7FFF7FFFu, kp.i[j] & 0x7FFF7FFFu));
        m = __reduce_max_sync(~0u, max(m << 16, m & 0xFFFF0000u));
        const uint32_t e = min(max(__float_as_uint(2.f * dt * __uint_as_float(m)) >> 23, 2u), 252u);
        cs = 2.f * dt * __uint_as_float((253u - e) << 23);
        if (lane == 0) sts32(dump + (2 * wg + half) * 3072, (e + 1u) << 23);
        an = kg_anchor_hi(kp, sel, dt, cs);
    } else {
        an = kg_anchor_lo(kp, sel, dt);
    }
    if (an.v[0] != 0xFFFFFFFFu) hook();
    float acc[24];
    const int nstep = wg == 2 ? 3 : 6;
#pragma unroll 1
    for (int c = 0; c < nstep; c++) {
        if (wg < 2) sel ^= 0x2200u;
        if (wg == 2 || (c & 1)) {
#pragma unroll
            for (int j = 0; j < 2; j++) { kp.l[j] = kp.l[j + 1]; kp.a[j] = kp.a[j + 1]; kp.r[j] = kp.r[j + 1]; kp.i[j] = kp.i[j + 1]; }
        }
        const uint32_t buf = scr + (2 * wg + (c & 1)) * 16384, tb = buf + lane * 128;
        if (!hi) {
            cpair p[4];
            p[0] = {an.v[0], an.v[1]}; p[1] = {an.v[2], an.v[3]};
            p[2] = pmul(p[0], an.v[4]); p[3] = pmul(p[1], an.v[4]);
#pragma unroll
            for (int j = 0; j < 4; j++) {
                cpair v[4];
#pragma unroll
                for (int i = 0; i < 4; i++) v[i] = j ? pmul(p[i], an.v[4 + j]) : p[i];
                const uint32_t a = tb + (((4 * half + j) ^ sw) << 4);
                sts128(a, make_uint4(v[0].r, v[1].r, v[2].r, v[3].r));
                sts128(a + 4096, make_uint4(v[0].i, v[1].i, v[2].i, v[3].i));
            }
            an = kg_anchor_lo(kp, sel, dt);
        } else {
            const uint32_t h1 = an.v[2], h2 = an.v[3], h256 = an.v[4], h512 = an.v[5], h1024 = an.v[6];
            cpair p[11];
            p[0] = {an.v[0], an.v[1]};
            p[1] = pmul(p[0], h2); p[2] = pmul(p[0], h1); p[3] = pmul(p[1], h1);
            p[4] = pmul(p[0], h256); p[5] = pmul(p[1], h256); p[6] = pmul(p[0], h512); p[7] = pmul(p[4], h512);
            p[8] = pmul({__byte_perm(p[0].r, p[4].r, 0x5410), __byte_perm(p[0].i, p[4].i, 0x5410)}, h1024);
            p[9] = pmul(p[8], h512); p[10] = pmul(p[8], h1024);
#pragma unroll
            for (int j = 0; j < 3; j++) {
                const uint32_t a = tb + 8192 + (((3 * half + j) ^ sw) << 4);
                sts128(a, make_uint4(p[4 * j].r, p[4 * j + 1].r, p[4 * j + 2].r, p[j < 2 ? 4 * j + 3 : 10].r));
                sts128(a + 4096, make_uint4(p[4 * j].i, p[4 * j + 1].i, p[4 * j + 2].i, p[j < 2 ? 4 * j + 3 : 10].i));
            }
            an = kg_anchor_hi(kp, sel, dt, cs);
        }
        if (c == 0) TS(24);
        if (c == 2) TS(26);
        fence_async_smem();
        wg_wait<0>();
        named_bar(5 + wg, 128);
        if (c == 1) TS(25);
        if (c == 2) TS(28);
        const uint64_t da = mkdesc(buf, 4096, 1024, 1);
        wg_fence();
#pragma unroll
        for (int k = 0; k < 4; k++) wgmma_kg(acc, da + k * 128, da + 512 + k * 128, k > 0 || c > 0);
        wg_commit();
    }
    const uint32_t ob = dump + (2 * wg + (hi ? 1 : 0)) * 3072, o = ob + ((16 * half + (lane >> 2)) * 24 + 2 * (lane & 3)) * 4;
    const float ci = __uint_as_float(lds32(ob));
    const float ds = (lane == 0 && warp <= 8 && !half) ? bf_lo(kp.ds) : 0.f;
    named_bar(5 + wg, 128);
    wg_wait<0>();
#pragma unroll
    for (int j = 0; j < 3; j++)
#pragma unroll
        for (int h = 0; h < 2; h++)
            asm volatile("st.shared.v2.f32 [%0], {%1, %2};" ::"r"(o + h * 768 + j * 32), "f"(fmaf(ci, hi ? acc[12 + 4 * j + 2 * h] : acc[4 * j + 2 * h], j + h ? 0.f : ds)),
                         "f"(ci * (hi ? acc[13 + 4 * j + 2 * h] : acc[4 * j + 2 * h + 1])) : "memory");
}

__device__ __forceinline__ void kgen_expand(int d0, uint32_t dump, KgShared* ks, int ht TS_ARG) {
    const int lane = ht & 31;
    auto F = [](uint32_t x) { return __uint_as_float(x); };
#pragma unroll 1
    for (int c = 0; c < 5; c++) {
        float m = 0.f;
#pragma unroll
        for (int i = 0; i < 2; i++) {
            const uint32_t a = dump + c * 3072 + (ht + 96 * i) * 16;
            const uint4 x = lds128(a), y = c == 4 ? lds128(a + 3072) : make_uint4(0, 0, 0, 0);
            const float v0 = F(x.x) + F(y.x), v1 = F(x.y) + F(y.y), v2 = F(x.z) + F(y.z), v3 = F(x.w) + F(y.w);
            if (c == 4) sts128(a, make_uint4(__float_as_uint(v0), __float_as_uint(v1), __float_as_uint(v2), __float_as_uint(v3)));
            m = fmaxf(fmaxf(m, fmaxf(fabsf(v0), fabsf(v1))), fmaxf(fabsf(v2), fabsf(v3)));
        }
        const uint32_t mm = __reduce_max_sync(~0u, __float_as_uint(m));
        if (lane == 0) asm volatile("red.shared.max.u32 [%0], %1;" ::"r"(s2u(&ks->kmax[c])), "r"(mm) : "memory");
    }
    named_bar(4, 96);
    TSX(2, 6);
#pragma unroll 1
    for (int task = ht >> 5; task < 20; task += 3) {
        const int c = task >> 2, it = (task & 3) * 32 + lane, a = it >> 2, d = d0 + c;
        const uint4 o0 = lds128(dump + KG_IDX + it * 16), o1 = lds128(dump + KG_IDX + 2048 + it * 16);
        const uint32_t e = min(max(ks->kmax[c] >> 23, 4u), 250u), b = dump + c * 3072;
        const float sc = __uint_as_float((253u - e) << 23);
        if (it == 0) g_ksc[d] = e;
        uint32_t ev[4], ov[4];
#pragma unroll
        for (int i = 0; i < 4; i++) {
            const float x0 = F(lds32(b + (u4(o0, i) & 0xFFFF))), x1 = F(lds32(b + (u4(o0, i) >> 16)));
            const float y0 = F(lds32(b + (u4(o1, i) & 0xFFFF))), y1 = F(lds32(b + (u4(o1, i) >> 16)));
            ev[i] = pack2h((x0 + y0) * sc, (x1 + y1) * sc);
            ov[i] = pack2h((x0 - y0) * sc, (x1 - y1) * sc);
        }
        uint32_t* dst = &g_keo[d >> 1][a * 32 + (((4 * (d & 1) + (it & 3)) ^ (a & 7)) << 2)];
        stg128(dst, make_uint4(ev[0], ev[1], ev[2], ev[3]));
        stg128(dst + 1024, make_uint4(ov[0], ov[1], ov[2], ov[3]));
    }
}
__device__ __forceinline__ void wgmma_h64_rs(uint32_t (&d)[16], const uint4& a, uint64_t db, int scale_d) {
    asm volatile("{\n.reg .pred p;\nsetp.ne.b32 p, %21, 0;\n"
                 "wgmma.mma_async.sync.aligned.m64n64k16.f16.f16.f16 {%0,%1,%2,%3,%4,%5,%6,%7,%8,%9,%10,%11,%12,%13,%14,%15}, {%16,%17,%18,%19}, %20, p, 1, 1, 1;\n}\n"
                 : "+r"(d[0]), "+r"(d[1]), "+r"(d[2]), "+r"(d[3]), "+r"(d[4]), "+r"(d[5]), "+r"(d[6]), "+r"(d[7]), "+r"(d[8]), "+r"(d[9]),
                   "+r"(d[10]), "+r"(d[11]), "+r"(d[12]), "+r"(d[13]), "+r"(d[14]), "+r"(d[15])
                 : "r"(a.x), "r"(a.y), "r"(a.z), "r"(a.w), "l"(db), "r"(scale_d));
}
__device__ __forceinline__ void wgmma_h32_rs(uint32_t (&d)[8], const uint32_t (&a)[4], uint64_t db, int scale_d) {
    asm volatile("{\n.reg .pred p;\nsetp.ne.b32 p, %13, 0;\n"
                 "wgmma.mma_async.sync.aligned.m64n32k16.f16.f16.f16 {%0,%1,%2,%3,%4,%5,%6,%7}, {%8,%9,%10,%11}, %12, p, 1, 1, 0;\n}\n"
                 : "+r"(d[0]), "+r"(d[1]), "+r"(d[2]), "+r"(d[3]), "+r"(d[4]), "+r"(d[5]), "+r"(d[6]), "+r"(d[7])
                 : "r"(a[0]), "r"(a[1]), "r"(a[2]), "r"(a[3]), "l"(db), "r"(scale_d));
}
__device__ __forceinline__ void wgmma_sp64_rs(float (&d)[32], const uint4& a, uint64_t db, uint32_t meta, int scale_d) {
    asm volatile("{\n.reg .pred p;\nsetp.ne.b32 p, %38, 0;\n"
                 "wgmma.mma_async.sp.sync.aligned.m64n64k32.f32.f16.f16 "
                 "{%0,%1,%2,%3,%4,%5,%6,%7,%8,%9,%10,%11,%12,%13,%14,%15,%16,%17,%18,%19,%20,%21,%22,%23,%24,%25,%26,%27,%28,%29,%30,%31}, "
                 "{%32,%33,%34,%35}, %36, %37, 0, p, 1, 1, 1;\n}\n"
                 : "+f"(d[0]), "+f"(d[1]), "+f"(d[2]), "+f"(d[3]), "+f"(d[4]), "+f"(d[5]), "+f"(d[6]), "+f"(d[7]), "+f"(d[8]), "+f"(d[9]),
                   "+f"(d[10]), "+f"(d[11]), "+f"(d[12]), "+f"(d[13]), "+f"(d[14]), "+f"(d[15]), "+f"(d[16]), "+f"(d[17]), "+f"(d[18]), "+f"(d[19]),
                   "+f"(d[20]), "+f"(d[21]), "+f"(d[22]), "+f"(d[23]), "+f"(d[24]), "+f"(d[25]), "+f"(d[26]), "+f"(d[27]), "+f"(d[28]), "+f"(d[29]),
                   "+f"(d[30]), "+f"(d[31])
                 : "r"(a.x), "r"(a.y), "r"(a.z), "r"(a.w), "l"(db), "r"(meta), "r"(scale_d));
}

__device__ __forceinline__ void fft_stage(const uint32_t (&u)[2][2][4], uint32_t eo, int warp4, int lane) {
    const int mi = lane >> 3, mj = lane & 7;
#pragma unroll
    for (int c = 0; c < 2; c++) {
        const uint32_t a = eo + (8 * warp4 + mj) * 128 + (((4 * c + mi) ^ mj) << 4);
        stsm_x4(a, hadd(u[c][0][0], u[c][1][0]), hadd(u[c][0][1], u[c][1][1]), hadd(u[c][0][2], u[c][1][2]), hadd(u[c][0][3], u[c][1][3]));
        stsm_x4(a + 4096, hsub(u[c][0][0], u[c][1][0]), hsub(u[c][0][1], u[c][1][1]), hsub(u[c][0][2], u[c][1][2]), hsub(u[c][0][3], u[c][1][3]));
    }
    fence_async_smem();
}
template <class Mid>
__device__ __forceinline__ void fft_forward(const uint4 (&a1)[4], const uint4 (&tw)[4], uint32_t eo, uint32_t s2, uint32_t (&X)[2][2][8], Mid mid) {
    uint32_t dr[16], di[16];
    const uint64_t de = mkdesc(eo, 4096, 1024, 1), d2 = mkdesc(s2, 16, 1024, 1);
    wg_fence();
    wgmma_h64_rs(dr, a1[0], de, 0);
    wgmma_h64_rs(di, a1[2], de + 256, 0);
    wgmma_h64_rs(dr, a1[1], de + 128, 1);
    wgmma_h64_rs(di, a1[3], de + 384, 1);
    wg_commit();
    mid();
    wg_wait<0>();
#pragma unroll
    for (int c = 0; c < 2; c++) {
        uint32_t zr[2][4], zi[2][4];
#pragma unroll
        for (int p = 0; p < 2; p++)
#pragma unroll
            for (int i = 0; i < 4; i++) {
                const uint32_t r = dr[8 * c + 4 * p + i], m = di[8 * c + 4 * p + i], tr = u4(tw[p], i), ti = u4(tw[2 + p], i);
                zr[p][i] = hfms(m, ti, hmul(r, tr));
                zi[p][i] = hfma(m, tr, hmul(r, ti));
            }
        wg_fence();
        wgmma_h32_rs(X[c][0], zr[0], d2, 0);
        wgmma_h32_rs(X[c][1], zr[1], d2 + 4, 0);
        wgmma_h32_rs(X[c][0], zi[0], d2 + 2, 1);
        wgmma_h32_rs(X[c][1], zi[1], d2 + 6, 1);
        wg_commit();
    }
}

template <class Mid, class Ready>
__device__ __forceinline__ void conv_pair(int ch0, int layer, uint32_t eo, uint32_t zb, uint32_t s23, uint32_t kbar, int warp, int lane,
                                          uint4 (&a1)[4], uint4 (&tw)[4], Mid mid, Ready ready TS_ARG) {
    const int wg = warp >> 2, w = warp & 3, t = 32 * w + lane, g = lane >> 2, q = lane & 3, mi = lane >> 3, mj = lane & 7;
    const bf16* xT = g_x1T;
    const float* sums = g_sums[layer][0];
    uint32_t u[2][2][4], KH[2][2][8];
    TS(1);
    mbar_wait(kbar, 0);
    TS(2);
    fft_forward(a1, tw, eo, s23, KH, mid);
    const uint2 ke = ldg64(g_ksc + ch0);
    named_bar(1 + wg, 128);
#pragma unroll
    for (int i = 0; i < 4; i++) tw[i] = ldg_tab(4 + i, t);
    const uint32_t oscale[2] = {(ke.x + 3u) * 0x00800080u, (ke.y + 3u) * 0x00800080u};
    wg_wait<0>();
    TS(4);
    ready();
    TS(5);
    uint2 x[2][2][2];
    const int ra[2] = {16 * (8 * w + g) + 4 * q, 16 * (63 - 8 * w - g) + 4 * q};
    {
        uint4 s[2][2][2];
#pragma unroll
        for (int h = 0; h < 2; h++)
#pragma unroll
            for (int p = 0; p < 2; p++) {
                s[h][p][0] = ldg128(sums + 1024 * p + ra[h]);
                s[h][p][1] = ldg128(sums + SEQ + 1024 * p + ra[h]);
#pragma unroll
                for (int c = 0; c < 2; c++) x[c][h][p] = ldg64(xT + (size_t)(ch0 + c) * XP + 1024 * p + ra[h]);
            }
        TS(6);
#pragma unroll
        for (int h = 0; h < 2; h++)
#pragma unroll
            for (int j = 0; j < 4; j++) {
                const uint4 sa = s[h][j >> 1][0], sq = s[h][j >> 1][1];
                const float4 v = make_float4(__uint_as_float(u4(sa, 2 * (j & 1))), __uint_as_float(u4(sq, 2 * (j & 1))),
                                             __uint_as_float(u4(sa, 2 * (j & 1) + 1)), __uint_as_float(u4(sq, 2 * (j & 1) + 1)));
                const float m0 = v.x * (1.0f / DM), m1 = v.z * (1.0f / DM);
                const float r0 = frsq(fmaxf(fmaf(v.y, 1.0f / DM, fmaf(-m0, m0, 1e-5f)), 1e-5f));
                const float r1 = frsq(fmaxf(fmaf(v.w, 1.0f / DM, fmaf(-m1, m1, 1e-5f)), 1e-5f));
                const float c0 = -m0 * r0, c1 = -m1 * r1;
#pragma unroll
                for (int c = 0; c < 2; c++) {
                    const uint32_t xv = (j & 1) ? x[c][h][j >> 1].y : x[c][h][j >> 1].x;
                    u[c][h][j] = pack2h(fmaf(bf_lo(xv), r0, c0), fmaf(bf_hi(xv), r1, c1));
                }
            }
    }
    TS(8);
    uint32_t X[2][2][8], Y[2][2][8];
    fft_stage(u, eo, w, lane);
    TS(9);
    named_bar(1 + wg, 128);
    fft_forward(a1, tw, eo, s23, X, [] {});
    TS(10);
#pragma unroll
    for (int i = 0; i < 4; i++) a1[i] = ldg_tab(12 + i, t);
    const uint64_t d3 = mkdesc(s23 + 4096, 16, 1024, 1);
#pragma unroll
    for (int c = 0; c < 2; c++) {
        wg_wait<1>();
        TS(11 + c);
        uint32_t pr[2][4], pi[2][4];
#pragma unroll
        for (int i = 0; i < 4; i++) {
            const uint32_t er = X[c][0][i], ei = X[c][0][4 + i], orr = X[c][1][i], oi = X[c][1][4 + i];
            const uint32_t ar = KH[c][0][i], ai = KH[c][0][4 + i], br = KH[c][1][i], bi = KH[c][1][4 + i];
            pr[0][i] = hfms(bi, oi, hfma(br, orr, hfms(ai, ei, hmul(ar, er))));
            pi[0][i] = hfma(bi, orr, hfma(br, oi, hfma(ai, er, hmul(ar, ei))));
            pr[1][i] = hfms(ai, oi, hfma(ar, orr, hfms(bi, ei, hmul(br, er))));
            pi[1][i] = hfma(ai, orr, hfma(ar, oi, hfma(bi, er, hmul(br, ei))));
        }
        wg_fence();
        wgmma_h32_rs(Y[c][0], pr[0], d3, 0);
        wgmma_h32_rs(Y[c][1], pr[1], d3 + 4, 0);
        wgmma_h32_rs(Y[c][0], pi[0], d3 + 2, 1);
        wgmma_h32_rs(Y[c][1], pi[1], d3 + 6, 1);
        wg_commit();
    }
#pragma unroll
    for (int c = 0; c < 2; c++) {
        if (c == 0) wg_wait<1>(); else wg_wait<0>();
        TS(13 + c);
        uint32_t zr[2][4], zi[2][4];
#pragma unroll
        for (int p = 0; p < 2; p++)
#pragma unroll
            for (int i = 0; i < 4; i++) {
                const uint32_t r = Y[c][p][i], m = Y[c][p][4 + i], tr = u4(tw[p], i), ti = u4(tw[2 + p], i);
                zr[i & 1][2 * p + (i >> 1)] = hfma(m, ti, hmul(r, tr));
                zi[i & 1][2 * p + (i >> 1)] = hfms(r, ti, hmul(m, tr));
            }
        const int kr = 4 * (mj >> 1) + (mj & 1) + 2 * (mj >> 2), ki = kr ^ 2;
#pragma unroll
        for (int h = 0; h < 2; h++) {
            const uint32_t a = zb + (2 * w + h) * 2048;
            stsm_x4(a + kr * 128 + (((4 * c + mi) ^ (kr & 7)) << 4), zr[h][0], zr[h][1], zr[h][2], zr[h][3]);
            stsm_x4(a + ki * 128 + (((4 * c + mi) ^ (ki & 7)) << 4), zi[h][0], zi[h][1], zi[h][2], zi[h][3]);
        }
    }
    TS(15);
    fence_async_smem();
    TS(16);
    named_bar(1 + wg, 128);
    TS(17);
    float acc[32];
    const uint64_t dz = mkdesc(zb, 4096, 1024, 1);
    wg_fence();
#pragma unroll
    for (int ks = 0; ks < 4; ks++) wgmma_sp64_rs(acc, a1[ks], dz + ks * 256, 0x44EEEE44u, ks > 0);
    wg_commit();
    wg_wait<0>();
    TS(18);
#pragma unroll
    for (int p = 0; p < 2; p++) {
        uint32_t r[2][2][2];
#pragma unroll
        for (int c = 0; c < 2; c++)
#pragma unroll
            for (int j = 0; j < 2; j++) {
                const float* d = acc + 4 * (4 * c + 2 * p + j);
                const uint32_t y0 = pack2(d[0] + d[2], d[1] + d[3]), y1 = pack2(d[0] - d[2], d[1] - d[3]);
                asm("fma.rn.bf16x2 %0, %1, %2, %3;" : "=r"(r[c][0][j]) : "r"(y0), "r"(oscale[c]), "r"(j ? x[c][0][p].y : x[c][0][p].x));
                asm("fma.rn.bf16x2 %0, %1, %2, %3;" : "=r"(r[c][1][j]) : "r"(y1), "r"(oscale[c]), "r"(j ? x[c][1][p].y : x[c][1][p].x));
            }
#pragma unroll
        for (int h = 0; h < 2; h++) {
            if (layer == 0) {
#pragma unroll
                for (int c = 0; c < 2; c++) *(uint2*)(g_x2T + (size_t)(ch0 + c) * XP + 1024 * p + ra[h]) = make_uint2(r[c][h][0], r[c][h][1]);
            } else {
                const uint32_t v0 = __byte_perm(r[0][h][0], r[1][h][0], 0x5410);
                st_ll4((uint4*)&g_fin[ch0 >> 1][1024 * p + ra[h]], v0 ? v0 : 0x80000000u, __byte_perm(r[0][h][0], r[1][h][0], 0x7632),
                       __byte_perm(r[0][h][1], r[1][h][1], 0x5410), __byte_perm(r[0][h][1], r[1][h][1], 0x7632));
            }
        }
    }
    TS(19);
}

#define Q_SCHED 0
#define Q_WAITFOR(it) (Q_SCHED == 0 ? (it) - 2 : Q_SCHED == 1 ? ((it) == 3 ? 1 : 0) : Q_SCHED == 2 ? -1 : (it) - 1)
#define Q_S0 8
#define Q_WGATE 0
#define FIN_SLEEP 100
#define F_WDELAY 1200
constexpr int Q_ST = 4;
constexpr int Q_AB = 16384, Q_BB = 30720, Q_SB = Q_AB + Q_BB;
constexpr int Q_EROW = 336;
constexpr int Q_ESLOT = 8 * Q_EROW;
constexpr int Q_EOFF = Q_ST * Q_SB;
constexpr int Q_KG = 2 * Q_SB;
constexpr int Q_KDUMP = Q_EOFF + 16384;
static_assert(6 * Q_ESLOT <= 16384, "exchange slots");
static_assert(Q_KG + KG_TABLES <= Q_KDUMP, "kernel generation layout");
constexpr int Q_SMEM = Q_KDUMP + KG_DUMP;
constexpr int F_EO = Q_EOFF, F_S23 = F_EO + 3 * 8192;
static_assert(F_S23 + 8192 <= Q_SMEM, "convolution layout");
__host__ __device__ constexpr int w_grp(int j) { return j < 7 ? 2 * Q_SB + j * 12800 : 20480; }
constexpr int W_RES = 0, W_OUT = Q_SB;

constexpr int Q_ZERO = Q_EOFF + 4096, Q_WOT = Q_EOFF + 8320;

__device__ unsigned g_epoch;
__device__ __align__(1024) unsigned g_bar[4][16][32];
__device__ __align__(1024) uint4 g_wop[8][80][10][8];
__device__ __align__(1024) uint4 g_csp[8][16][96];
__device__ __align__(1024) uint4 g_stp[16][8][64];
__device__ __align__(1024) uint4 g_halo[128][2][5][32];
__device__ __align__(1024) uint4 g_of[8][16][8][5][32];

struct Bars { uint64_t full[Q_ST], empty[Q_ST], wfull[3], ex[8], res, go, qdone, att, prep, kf, ardy, hdone, fdone, idx, kdone, att1; };
constexpr int NBAR = sizeof(Bars) / 8;
__device__ __forceinline__ void grid_wait(const unsigned* c, int n, unsigned target, int lane) {
    const unsigned* p = c + 32 * min(lane, n - 1);
    unsigned v;
    int spin = 0;
    do { asm volatile("ld.relaxed.gpu.global.u32 %0, [%1];" : "=r"(v) : "l"(p) : "memory"); } while (!__all_sync(~0u, (int)(v - target) >= 0) && ++spin < (1 << 18));
    fence_acquire();
}
__device__ __forceinline__ void grid_arrive(unsigned* c) {
    fence_release();
    asm volatile("red.relaxed.gpu.global.add.u32 [%0], 1;" ::"l"(c) : "memory");
}

#define TMAP(n) ([] { const CUtensorMap* p_; asm volatile("{\n.reg .b64 t;\nmov.b64 t, fused_kernel_param_" #n ";\ncvta.param.u64 %0, t;\n}" : "=l"(p_)); return p_; }())
extern "C" __global__ void __launch_bounds__(384, 1)
fused_kernel(const __grid_constant__ CUtensorMap mX0, const __grid_constant__ CUtensorMap mX1, const __grid_constant__ CUtensorMap mW,
             const __grid_constant__ CUtensorMap mWr,
             const __grid_constant__ CUtensorMap mRes0, const __grid_constant__ CUtensorMap mRes1, const __grid_constant__ CUtensorMap mOut,
             const __grid_constant__ CUtensorMap mWo, bf16* __restrict__ out, const SsmParams sp) {
    extern __shared__ __align__(1024) char smraw[];
    __shared__ __align__(8) Bars s_bar[2];
    __shared__ __align__(16) float s_cs[240], s_mean[2][72], s_rstd[2][72];
    __shared__ KgShared s_kg;
    __shared__ uint32_t s_epoch;
    const uint32_t sb = s2u(smraw);
    int tid, warp, lane, bx, rank, blk, hg, npair, pair0, rot, c0;
    auto indices = [&] {
        asm volatile("mov.u32 %0, %%tid.x;" : "=r"(tid));
        asm volatile("mov.u32 %0, %%ctaid.x;" : "=r"(bx));
        warp = __shfl_sync(~0u, tid >> 5, 0); lane = tid & 31;
        rank = bx & 1; blk = bx & 15; hg = bx >> 4;
        npair = 3 - rank; pair0 = 5 * (bx >> 1) + 3 * rank;
        const int u = ((blk >> 1) + hg) & 7;
        rot = (5 * u) >> 2; c0 = 16 * (u & 3);
    };
    indices();
    TS_DECL;
    TS_BEGIN;
    KgParams kp;
    kgen_load(kp, bx * 5, warp, lane, sp);
    const uint32_t epoch0 = ldg32(&g_epoch);
#define EPOCH lds32(s2u(&s_epoch))
    if (tid < 64) g_sums[0][0][64 * bx + tid] = 0.f;
    if (tid < 5) s_kg.kmax[tid] = 0u;
    if (tid == 256) { prefetch_tmap(TMAP(2)); prefetch_tmap(TMAP(3)); prefetch_tmap(TMAP(0)); prefetch_tmap(TMAP(7)); }
    if (tid == 320) { prefetch_tmap(TMAP(4)); prefetch_tmap(TMAP(6)); prefetch_tmap(TMAP(1)); prefetch_tmap(TMAP(5)); }
    if (tid < 260) sts128(sb + Q_ZERO + tid * 16, make_uint4(0, 0, 0, 0));
    if (elect_one()) {
#define BAR_IS(f) (i == offsetof(Bars, f) / 8)
#pragma unroll 1
        for (int i = warp; i < NBAR; i += 12) {
            const int cnt = (i >= 4 && i < 8) ? 16 : (BAR_IS(go) || BAR_IS(att1)) ? 4 : (BAR_IS(qdone) || BAR_IS(att)) ? 8 : BAR_IS(prep) ? 96 : BAR_IS(hdone) ? 6 : BAR_IS(fdone) ? npair : BAR_IS(kdone) ? 2 : 1;
            mbar_init(s2u(s_bar) + i * 8, cnt);
            mbar_init(s2u(s_bar) + (NBAR + i) * 8, cnt);
        }
        fence_mbar_init();
    }
    __syncwarp();
    TS(29);
    fence_async_smem();
    TS(30);
    __syncthreads();
    TS(31);
    cluster_arrive_relaxed();
    cluster_wait();
    TS(27);

    int layer = 0;
    uint32_t bars = s2u(s_bar);
#define BAR(f) (bars + (uint32_t)offsetof(Bars, f))
    auto issue_w = [&](uint32_t bb, int it, int half) {
        const int s = it & (Q_ST - 1);
        const uint32_t fb = bb + 8 * s, db = sb + s * Q_SB + Q_AB + half * 15360;
        const int k0 = (it + rot - (it + rot >= 10 ? 10 : 0)) * 64 + half * 32;
#pragma unroll
        for (int p = 0; p < 3; p++) tma2d_mc(db + p * 4096, TMAP(2), p * DM + hg * 80, k0, fb, 3);
        tma3d_mc(db + 12288, TMAP(3), hg * 80 + 64, k0, 0, fb, 3);
    };
    auto issue_x = [&](int it) {
        const int s = it & (Q_ST - 1), kc = it + rot - (it + rot >= 10 ? 10 : 0);
        mbar_expect(BAR(full) + 8 * s, Q_SB);
        tma3d(sb + s * Q_SB, TMAP(0) + layer, (layer ? blk : kc) * 64, (layer ? kc : blk) * 64, 0, BAR(full) + 8 * s);
    };
    {
        if (warp == 8) {
            if (elect_one()) {
#pragma unroll 1
                for (int it = 0; it < 2; it++) { issue_w(BAR(full), it, rank); issue_x(it); }
                mbar_expect(BAR(idx), 4096 + 6400);
                bulk_g2s(sb + Q_KDUMP + KG_IDX, c_fft + 16 * 512, 4096, BAR(idx));
                asm volatile("cp.async.bulk.tensor.4d.shared::cluster.global.mbarrier::complete_tx::bytes [%0], [%1, {0, 0, %3, %4}], [%2];"
                             ::"r"(sb + Q_WOT), "l"(TMAP(7)), "r"(BAR(idx)), "r"(10 * hg), "r"(5 * blk) : "memory");
                prefetch_l2((const char*)c_fft + bx * (sizeof(c_fft) / 128), sizeof(c_fft) / 128);
            }
            __syncwarp();
        }
        kgen_tables(kp, sb + Q_KG, sb + Q_KDUMP, warp, lane, [&] {
            if (tid == 256) s_epoch = epoch0;
        } TS_PASS);
        if (warp <= 8) asm volatile("bar.arrive 8, 384;" ::: "memory");
        fence_async_smem();
        cluster_arrive_relaxed();
        TS(1);
    }

#pragma unroll 1
    for (; layer < 2; layer++, bars += sizeof(Bars)) {
    indices();
    TS_PHASE(2 * layer);
    uint4 fa1[4], ftw[4];
    auto conv_tables = [&] {
#pragma unroll
        for (int i = 0; i < 4; i++) { fa1[i] = ldg_tab(i, tid & 127); ftw[i] = ldg_tab(8 + i, tid & 127); }
    };
    if (warp >= 8) {
        asm volatile("setmaxnreg.dec.sync.aligned.u32 88;");
        if (warp == 8) {
            if (layer == 0) {
                cluster_wait();
            } else {
                grid_wait(g_bar[2][0], 10, 32 * (EPOCH + 1), lane);
                mbar_wait(BAR(fdone) - sizeof(Bars), 0);
                fence_async_global();
                TS(1);
            }
            if (elect_one()) {
#pragma unroll 1
                for (int it = layer ? 0 : 2; it < 10; it++) {
                    if (it >= Q_ST) mbar_wait(BAR(empty) + 8 * (it & (Q_ST - 1)), ((it >> 2) - 1) & 1);
                    else if (it > 0 && Q_WAITFOR(it) >= 0) mbar_wait(BAR(full) + 8 * Q_WAITFOR(it), 0);
                    if (it == Q_ST) mbar_wait(BAR(hdone), 0);
                    issue_x(it);
                    if (it >= Q_ST || layer == 0) issue_w(BAR(full), it, rank);
                }
                if (layer == 0) { mbar_wait(BAR(prep), 0); fence_async_global(); }
#pragma unroll 1
                for (int j = 0; j < 8; j++) {
                    const int b = (j + 1) >> 2;
                    const uint32_t fb = BAR(wfull) + 8 * b;
                    if (j == 0 || j == 3 || j == 7) {
                        mbar_wait(BAR(empty) + 8 * ((2 + b) & 3), b < 2);
                        TS(11 + b);
                        mbar_expect(fb, (b == 0 ? 3 : b == 1 ? 4 : 1) * 12800);
                    }
                    bulk_g2s_mc(sb + w_grp(j) + rank * 6400, &g_wop[hg][((hg + j) & 7) * 10 + rank * 5], 6400, fb, 3);
                }
                mbar_expect(BAR(res), 20480);
                if (layer == 0) tma3d(sb + W_RES, TMAP(0), hg * 80, blk * 64, 0, BAR(res));
                tma3d(sb + W_RES + (layer ? 0 : 16384), TMAP(4) + layer, layer ? blk * 64 : hg * 80 + 64, layer ? hg * 80 : blk * 64, 0, BAR(res));
                if (layer == 0) { mbar_wait(BAR(kdone), 0); fence_async_global(); }
                mbar_wait(BAR(att), 0);
                mbar_expect(BAR(kf), (npair + 1 - layer) * 8192);
                bulk_g2s(sb + F_EO, g_keo[pair0], npair * 8192, BAR(kf));
                if (layer == 0) bulk_g2s(sb + F_S23, c_fft + 18 * 512, 8192, BAR(kf));
            }
            __syncwarp();
        } else {
            const int ht = tid - 288, hw = warp - 9, mi = lane >> 3, mj = lane & 7, g = lane >> 2, q = lane & 3;
            auto F = [](uint32_t x) { return __uint_as_float(x); };
            auto U = [](float x) { return __float_as_uint(x); };
            const uint32_t lb = layer ^ 1, eb = ~EPOCH & 1u;
            if (layer == 0) {
                mbar_wait(BAR(idx), 0);
                if (hw == 2 && elect_one()) {
                    bulk_s2g(&g_wop[hg][5 * blk], sb + Q_WOT, 6400);
#pragma unroll 1
                    for (int i = 0; i < 5; i++) bulk_s2g((char*)g_fin + (bx * 5 + i) * (FP * 2), sb + Q_ZERO, FP * 2);
                    bulk_commit();
                }
                __syncwarp();
            }
            mbar_wait(BAR(full), 0);
            mbar_wait(BAR(full) + 8, 0);
            if (ht == 0) TSX(2, 2);
            if (layer == 0) {
                float cs[2][4] = {{0.f, 0.f, 0.f, 0.f}, {0.f, 0.f, 0.f, 0.f}};
#pragma unroll
                for (int G = 0; G < 5; G++) {
                    const int row = c0 + 40 * rank + 8 * G + mj;
                    const uint32_t b = sb + (row >> 6) * Q_SB + Q_AB + ((row >> 5) & 1) * 15360;
                    uint32_t r[10];
                    ldsm_x4_t(r[0], r[1], r[2], r[3], b + hw * 4096 + (row & 31) * 128 + ((mi ^ mj) << 4));
                    ldsm_x4_t(r[4], r[5], r[6], r[7], b + hw * 4096 + (row & 31) * 128 + (((4 + mi) ^ mj) << 4));
                    ldsm_x2_t(r[8], r[9], b + 12288 + hw * 1024 + (row & 31) * 32 + (((mi & 1) ^ (mj >> 2)) << 4));
#pragma unroll
                    for (int f = 0; f < 10; f += 2) {
                        const uint32_t a = g == (f & 7) ? 0x3F803F80u : 0u, c = g == (f & 7) + 1 ? 0x3F803F80u : 0u;
                        mma16816(cs[(f >> 1) & 1], f < 8 ? a : 0u, f < 8 ? 0u : a, f < 8 ? c : 0u, f < 8 ? 0u : c, r[f], r[f + 1]);
                    }
                }
                st_ll4(&g_csp[hg][blk][ht], (U(cs[0][0] + cs[1][0]) & ~1u) | eb, U(cs[0][1] + cs[1][1]), U(cs[0][2] + cs[1][2]), U(cs[0][3] + cs[1][3]));
            }
            uint32_t xf[3][20];
#pragma unroll
            for (int i = 0; i < 3; i++) {
                const int tile = min(hw + 3 * i, 7);
#pragma unroll
                for (int k = 0; k < 5; k++) {
                    const int ch = c0 + 16 * k + 8 * (mi >> 1), tok = 16 * (tile & 3) + 8 * (mi & 1);
                    const uint32_t a = sb + (ch >> 6) * Q_SB + (tile >> 2) * 8192;
                    if (layer == 0) ldsm_x4(xf[i][4 * k], xf[i][4 * k + 1], xf[i][4 * k + 2], xf[i][4 * k + 3], a + (tok + mj) * 128 + ((((ch & 63) >> 3) ^ mj) << 4));
                    else ldsm_x4_t(xf[i][4 * k], xf[i][4 * k + 1], xf[i][4 * k + 2], xf[i][4 * k + 3], a + ((ch & 63) + mj) * 128 + (((tok >> 3) ^ mj) << 4));
                }
            }
            fence_async_smem();
            __syncwarp();
            if (lane == 0) { mbar_arrive_cta(BAR(hdone), 0); mbar_arrive_cta(BAR(hdone), 1); }
            if (ht == 0) TSX(2, 3);
            if (layer == 0) {
                if (hw == 2 && elect_one()) { bulk_wait(); fence_async_global(); grid_arrive(g_bar[3][hg]); }
                __syncwarp();
                cluster_wait();
                named_bar(8, 384);
            }
            if (ht == 0) TSX(2, 8);
#pragma unroll
            for (int i = 0; i < 3; i++) {
                float a[4] = {0.f, 0.f, 0.f, 0.f};
#pragma unroll
                for (int j = 0; j < 20; j++) {
                    const float lo = bf_lo(xf[i][j]), hi = bf_hi(xf[i][j]);
                    a[2 * (j & 1)] += lo + hi; a[2 * (j & 1) + 1] = fmaf(lo, lo, fmaf(hi, hi, a[2 * (j & 1) + 1]));
                }
#pragma unroll
                for (int j = 0; j < 4; j++) { a[j] += __shfl_xor_sync(~0u, a[j], 1); a[j] += __shfl_xor_sync(~0u, a[j], 2); }
                if (q == 0 && hw + 3 * i < 8) st_ll4(&g_stp[blk][hg][8 * (hw + 3 * i) + g], (U(a[0]) & ~1u) | lb, U(a[1]), U(a[2]), U(a[3]));
            }
            if (ht == 0) TSX(2, 4);
            if (layer == 0) {
                float t[4] = {0.f, 0.f, 0.f, 0.f};
                uint4 v[16];
                int spin = 0;
                uint32_t bad;
                do {
                    bad = 0;
#pragma unroll
                    for (int j = 0; j < 16; j++) v[j] = ld_ll4(&g_csp[hg][j][ht]);
#pragma unroll
                    for (int j = 0; j < 16; j++) bad |= v[j].x ^ eb;
                } while ((bad & 1u) && ++spin < (1 << 18));
#pragma unroll
                for (int j = 0; j < 16; j++) { t[0] += F(v[j].x); t[1] += F(v[j].y); t[2] += F(v[j].z); t[3] += F(v[j].w); }
                *(float2*)&s_cs[80 * hw + 2 * lane] = make_float2(t[0], t[1]);
                if (lane < 8) *(float2*)&s_cs[80 * hw + 64 + 2 * lane] = make_float2(t[2], t[3]);
                if (hw == 2) grid_wait(g_bar[3][0], 8, 16 * (EPOCH + 1), lane);
            }
            if (ht == 0) TSX(2, 15);
            if (ht < 80) {
                const bool halo = ht >= 64;
                const int p = halo ? (ht >> 3) & 1 : ht >> 5, i = halo ? (ht & 7) - 8 : 8 + 2 * (ht & 24) + (ht & 7);
                const uint4* src = &g_stp[halo && blk ? blk - 1 : blk][0][halo ? 32 * p + 24 + (ht & 7) : ht];
                uint4 v[8];
                int spin = 0;
                uint32_t bad;
                do {
                    bad = 0;
#pragma unroll
                    for (int j = 0; j < 8; j++) v[j] = ld_ll4(src + 64 * j);
#pragma unroll
                    for (int j = 0; j < 8; j++) bad |= v[j].x ^ lb;
                } while ((bad & 1u) && ++spin < (1 << 18));
                float t[4] = {0.f, 0.f, 0.f, 0.f};
#pragma unroll
                for (int j = 0; j < 8; j++) { t[0] += F(v[j].x); t[1] += F(v[j].y); t[2] += F(v[j].z); t[3] += F(v[j].w); }
                const uint32_t s0 = ln_finish_packed(t[0], t[1]), s1 = ln_finish_packed(t[2], t[3]);
                if (!halo) { s_mean[p][i] = bf_hi(s0); s_rstd[p][i] = frcp(bf_lo(s0)); }
                s_mean[p][i + 8] = bf_hi(s1); s_rstd[p][i + 8] = frcp(bf_lo(s1));
            }
            fence_acquire();
            mbar_arrive(BAR(prep));
            if (ht == 0) TSX(2, 5);
            if (layer == 0) {
                __syncwarp();
                kgen_expand(bx * 5, sb + Q_KDUMP, &s_kg, ht TS_PASS);
                fence_async_smem();
                named_bar(4, 96);
                if (ht == 0) { fence_release(); mbar_arrive_cta(BAR(kdone), 0); mbar_arrive_cta(BAR(kdone), 1); }
                if (ht == 0) TSX(2, 7);
            }
        }
        __syncwarp();
        named_bar(3, 128);
        conv_tables();
        asm volatile("setmaxnreg.inc.sync.aligned.u32 168;");
    } else {
    const int wg = warp >> 2, w = warp & 3;
    const int mi = lane >> 3, mj = lane & 7, g = lane >> 2, q = lane & 3;
    TS(2);
    float acc[120];
#pragma unroll
    for (int i = 0; i < 120; i++) acc[i] = 0.f;
    auto release = [&](int it) {
        if (lane == 0) { mbar_arrive_cta(BAR(empty) + 8 * (it & (Q_ST - 1)), 0); mbar_arrive_cta(BAR(empty) + 8 * (it & (Q_ST - 1)), 1); }
    };
#pragma unroll 1
    for (int it = 0; it < 10; it++) {
        const int s = it & (Q_ST - 1);
        const uint32_t st = sb + s * Q_SB;
        const bool hold = wg == 1 && it == Q_S0;
        if (hold) {
            wg_wait<0>();
            release(it - 1);
            mbar_wait(BAR(go), 0);
        }
        mbar_wait(BAR(full) + 8 * (s), (it >> 2) & 1);
        if (it < 2) TS(3 + it);
        if (it == 6) TS(5);
        if (it == 9) TS(6);
        const uint64_t da = mkdesc(st + wg * 8192, 16, 1024, 1);
        const uint64_t db = mkdesc(st + Q_AB, 4096, 1024, 1);
        const uint64_t dr = mkdesc(st + Q_AB + 12288, 1024, 256, 3);
        if (layer == 0) {
            wg_fence();
#pragma unroll
            for (int ks = 0; ks < 4; ks++) {
                const int sc = 1;
                wgmma_n192<0, 1>(*(float(*)[96]) & acc[0], da + ks * 2, db + (ks >> 1) * 960 + (ks & 1) * 128, sc);
                wgmma_n48<0, 1>(*(float(*)[24]) & acc[96], da + ks * 2, dr + (ks >> 1) * 960 + (ks & 1) * 32, sc);
            }
            wg_commit();
        } else {
            wg_fence();
#pragma unroll
            for (int ks = 0; ks < 4; ks++) {
                const int sc = 1;
                wgmma_n192<1, 1>(*(float(*)[96]) & acc[0], da + ks * 128, db + (ks >> 1) * 960 + (ks & 1) * 128, sc);
                wgmma_n48<1, 1>(*(float(*)[24]) & acc[96], da + ks * 128, dr + (ks >> 1) * 960 + (ks & 1) * 32, sc);
            }
            wg_commit();
        }
        wg_wait<1>();
        if (it > 0 && !hold) release(it - 1);
    }
    if (wg == 0 && lane == 0) mbar_arrive(BAR(go));
    asm volatile("setmaxnreg.inc.sync.aligned.u32 208;");
    if (layer == 0) cluster_wait();
    mbar_wait(BAR(prep), 0);
    const uint32_t ob = layer ^ 1;
    const bool first = (blk == 0 && w == 0);
    const bool sel0 = (2 * q > g), sel1 = (2 * q + 1 > g);
    constexpr float SC = 0.22360679774997896f * 1.4426950408889634f;
    const float m0 = s_mean[wg][8 + 16 * w + g], m1 = s_mean[wg][16 + 16 * w + g];
    const float* rs = &s_rstd[wg][16 * w];
    const float kx0 = rs[2 * q + (sel0 ? 0 : 8)], kx1 = rs[2 * q + (sel1 ? 1 : 9)], ky0 = rs[2 * q + (sel0 ? 8 : 16)], ky1 = rs[2 * q + (sel1 ? 9 : 17)];
    const float cx0 = SC * rs[8 + g] * kx0, cx1 = SC * rs[8 + g] * kx1, cy0 = SC * rs[16 + g] * ky0, cy1 = SC * rs[16 + g] * ky1;
    wg_wait<0>();
    TS(7);
    if (lane == 0) mbar_arrive(BAR(qdone));
    uint32_t ql[10], qh[10], kl[10], kh[10], vl[10], vh[10];
    auto fold = [&](int p, int f, uint32_t& lo, uint32_t& hi) {
        const int j = (f < 8) ? 8 * p + f : 24 + 2 * p + (f - 8);
        const float2 c = *(const float2*)&s_cs[p * 80 + 8 * f + 2 * q];
        lo = pack2(fmaf(-m0, c.x, acc[4 * j]), fmaf(-m0, c.y, acc[4 * j + 1]));
        hi = pack2(fmaf(-m1, c.x, acc[4 * j + 2]), fmaf(-m1, c.y, acc[4 * j + 3]));
    };
#pragma unroll
    for (int f = 0; f < 10; f++) { fold(1, f, kl[f], kh[f]); fold(2, f, vl[f], vh[f]); }
    if (w == 3) {
        uint4* hp = &g_halo[bx][wg][0][lane];
#pragma unroll
        for (int f = 0; f < 5; f++) st_ll4(hp + 32 * f, (vh[2 * f] & ~1u) | ob, vh[2 * f + 1], kh[2 * f], kh[2 * f + 1]);
    } else {
        const uint32_t a = sb + Q_EOFF + (warp - wg) * Q_ESLOT + mj * Q_EROW + mi * 16;
        stsm_x4(a, kh[0], kh[1], kh[2], kh[3]);
        stsm_x4(a + 64, kh[4], kh[5], kh[6], kh[7]);
        stsm_x4(a + 128, kh[8], kh[9], vh[0], vh[1]);
        stsm_x4(a + 192, vh[2], vh[3], vh[4], vh[5]);
        stsm_x4(a + 256, vh[6], vh[7], vh[8], vh[9]);
        __syncwarp();
        if (lane == 0) mbar_arrive(BAR(ex) + 8 * (warp));
    }
    TS(9);
#pragma unroll
    for (int f = 0; f < 10; f++) fold(0, f, ql[f], qh[f]);
    uint32_t vt1[10], vt2[10];
#pragma unroll
    for (int f = 0; f < 10; f++) { vt1[f] = movm_t(vl[f]); vt2[f] = movm_t(vh[f]); }
    TS(10);
    uint32_t kp[10], vp[10];
    if (w > 0) {
        const uint32_t a = sb + Q_EOFF + (warp - wg - 1) * Q_ESLOT + mj * Q_EROW + mi * 16;
        mbar_wait(BAR(ex) + 8 * (warp - 1), 0);
        ldsm_x4(kp[0], kp[1], kp[2], kp[3], a);
        ldsm_x4(kp[4], kp[5], kp[6], kp[7], a + 64);
        ldsm_x2(kp[8], kp[9], a + 128);
        ldsm_x4_t(vp[0], vp[1], vp[2], vp[3], a + 160);
        ldsm_x4_t(vp[4], vp[5], vp[6], vp[7], a + 224);
        ldsm_x2_t(vp[8], vp[9], a + 288 - (lane >> 4) * 32);
    } else if (blk > 0) {
        const uint4* hp = &g_halo[bx - 1][wg][0][lane];
        uint4 hv[5];
        int spin = 0;
        uint32_t bad;
        do {
            bad = 0;
#pragma unroll
            for (int f = 0; f < 5; f++) hv[f] = ld_ll4(hp + 32 * f);
#pragma unroll
            for (int f = 0; f < 5; f++) bad |= hv[f].x ^ ob;
        } while (__any_sync(~0u, bad & 1u) && ++spin < (1 << 18));
#pragma unroll
        for (int f = 0; f < 10; f++) { kp[f] = u4(hv[f >> 1], 2 + (f & 1)); vp[f] = movm_t(u4(hv[f >> 1], f & 1)); }
    } else {
#pragma unroll
        for (int f = 0; f < 10; f++) { kp[f] = 0u; vp[f] = 0u; }
    }
    fence_async_smem();
    __syncwarp();
    if (lane == 0) mbar_arrive(BAR(att));
    TS(12);
    float oacc[10][4];
#pragma unroll
    for (int h = 0; h < 4; h++) {
        const int fa = (h == 0) ? 0 : (h == 1) ? 3 : (h == 2) ? 5 : 8, fb = fa + 1, fh = (h < 2) ? 2 : 7;
        const bool mine = (h & 1) ? (q >= 2) : (q < 2);
        const uint32_t qml = mine ? ql[fh] : 0u, qmh = mine ? qh[fh] : 0u;
        float S0[4] = {0.f, 0.f, 0.f, 0.f}, S1[4] = {0.f, 0.f, 0.f, 0.f}, S2[4] = {0.f, 0.f, 0.f, 0.f};
        mma16816(S0, ql[fa], qh[fa], ql[fb], qh[fb], kp[fa], kp[fb]); mma1688(S0, qml, qmh, kp[fh]);
        mma16816(S1, ql[fa], qh[fa], ql[fb], qh[fb], kl[fa], kl[fb]); mma1688(S1, qml, qmh, kl[fh]);
        mma16816(S2, ql[fa], qh[fa], ql[fb], qh[fb], kh[fa], kh[fb]); mma1688(S2, qml, qmh, kh[fh]);
        float x0 = (sel0 ? S0[0] : S1[0]) * cx0, x1 = (sel1 ? S0[1] : S1[1]) * cx1;
        float y0 = (sel0 ? S1[2] : S2[2]) * cy0, y1 = (sel1 ? S1[3] : S2[3]) * cy1;
        if (first) { if (sel0) x0 = -INFINITY; if (sel1) x1 = -INFINITY; }
        float mx = fmaxf(x0, x1), my = fmaxf(y0, y1);
        mx = fmaxf(mx, __shfl_xor_sync(~0u, mx, 1)); my = fmaxf(my, __shfl_xor_sync(~0u, my, 1));
        mx = fmaxf(mx, __shfl_xor_sync(~0u, mx, 2)); my = fmaxf(my, __shfl_xor_sync(~0u, my, 2));
        x0 = ex2(x0 - mx); x1 = ex2(x1 - mx); y0 = ex2(y0 - my); y1 = ex2(y1 - my);
        float sx = x0 + x1, sy = y0 + y1;
        sx += __shfl_xor_sync(~0u, sx, 1); sy += __shfl_xor_sync(~0u, sy, 1);
        sx += __shfl_xor_sync(~0u, sx, 2); sy += __shfl_xor_sync(~0u, sy, 2);
        const float ix = frcp(sx), iy = frcp(sy);
        x0 *= ix * kx0; x1 *= ix * kx1; y0 *= iy * ky0; y1 *= iy * ky1;
        const uint32_t pa0 = pack2(sel0 ? x0 : 0.f, sel1 ? x1 : 0.f);
        const uint32_t pa2 = pack2(sel0 ? 0.f : x0, sel1 ? 0.f : x1);
        const uint32_t pa3 = pack2(sel0 ? y0 : 0.f, sel1 ? y1 : 0.f);
        const uint32_t pb1 = pack2(sel0 ? 0.f : y0, sel1 ? 0.f : y1);
#pragma unroll
        for (int i = 0; i < 3; i++) {
            const int f = (i == 0) ? fa : (i == 1) ? fb : fh;
            float O[4] = {0.f, 0.f, 0.f, 0.f};
            mma16816(O, pa0, 0u, pa2, pa3, vp[f], vt1[f]);
            mma1688(O, 0u, pb1, vt2[f]);
            if (i < 2 || !(h & 1) || mine) { oacc[f][0] = O[0]; oacc[f][1] = O[1]; oacc[f][2] = O[2]; oacc[f][3] = O[3]; }
        }
    }
    TS(13);
    uint4 of[7][5];
    {
        uint4* dst = &g_of[hg][blk][warp][0][lane];
#pragma unroll
        for (int k = 0; k < 5; k++) {
            of[0][k] = make_uint4(pack2(oacc[2 * k][0], oacc[2 * k][1]), pack2(oacc[2 * k][2], oacc[2 * k][3]),
                                  pack2(oacc[2 * k + 1][0], oacc[2 * k + 1][1]), pack2(oacc[2 * k + 1][2], oacc[2 * k + 1][3]));
            st_ll4(dst + 32 * k, (of[0][k].x & ~1u) | ob, of[0][k].y, of[0][k].z, of[0][k].w);
        }
    }
    if (Q_WGATE && wg == 1 && lane == 0) mbar_arrive(BAR(att1));
    TS(14);
    const uint4* osrc = &g_of[0][blk][warp][0][lane];
    auto oload = [&](int j) {
        const uint4* p = osrc + ((hg + j) & 7) * 20480;
#pragma unroll
        for (int k = 0; k < 5; k++) of[j % 7][k] = ld_ll4(p + 32 * k);
    };
    float aw[40];
    auto omma = [&](int j) {
        const uint64_t dm = mkdesc(sb + w_grp(j), 1280, 128, 0);
        wg_fence();
#pragma unroll
        for (int k = 0; k < 5; k++) wgmma_rs80(aw, of[j % 7][k], dm + k * 160, j + k > 0);
        wg_commit();
    };
    if (Q_WGATE && wg == 0) mbar_wait(BAR(att1), 0);
    mbar_wait(BAR(wfull), 0);
    omma(0);
    {
        const uint32_t* pp = &g_of[(hg + 1 + min(lane, 6)) & 7][blk][warp][4][31].x;
        uint32_t v, m;
        int spin = 0;
        do {
            asm volatile("ld.relaxed.gpu.global.u32 %0, [%1];" : "=r"(v) : "l"(pp) : "memory");
            m = __ballot_sync(~0u, (v & 1u) != ob);
        } while ((m & 15u) && ++spin < (1 << 18));
        TS(15);
#pragma unroll
        for (int j = 1; j < 5; j++) oload(j);
        while (m && ++spin < (1 << 18)) {
            asm volatile("ld.relaxed.gpu.global.u32 %0, [%1];" : "=r"(v) : "l"(pp) : "memory");
            m = __ballot_sync(~0u, (v & 1u) != ob);
        }
        wg_wait<0>();
#pragma unroll
        for (int j = 5; j < 8; j++) oload(j);
        TS(16);
    }
#pragma unroll
    for (int j = 1; j < 8; j++) {
        if (j == 3 || j == 7) mbar_wait(BAR(wfull) + 8 * ((j + 1) >> 2), 0);
        int spin = 0;
        while (true) {
            const uint4* f = of[j % 7];
            const uint32_t bad = ((f[0].x ^ ob) | (f[1].x ^ ob) | (f[2].x ^ ob) | (f[3].x ^ ob) | (f[4].x ^ ob)) & 1u;
            if (__all_sync(~0u, !bad) || ++spin >= (1 << 18)) break;
            oload(j);
        }
        if (j == 1) TS(17);
        if (j == 5) TS(18);
        omma(j);
    }
    wg_wait<2>();
    uint32_t res[20];
    mbar_wait(BAR(res), 0);
    const uint32_t ta = (8 * (mi >> 1) + mj) * 128 + (((2 * w + (mi & 1)) ^ mj) << 4);
    if (layer == 0) {
        const int tok = 16 * w + 8 * (mi & 1) + mj;
#pragma unroll
        for (int k = 0; k < 4; k++)
            ldsm_x4(res[4 * k], res[4 * k + 1], res[4 * k + 2], res[4 * k + 3], sb + W_RES + wg * 8192 + tok * 128 + (((2 * k + (mi >> 1)) ^ mj) << 4));
        ldsm_x4(res[16], res[17], res[18], res[19], sb + W_RES + 16384 + wg * 2048 + tok * 32 + (((mi >> 1) ^ (mj >> 2)) << 4));
    } else {
#pragma unroll
        for (int k = 0; k < 5; k++) ldsm_x4_t(res[4 * k], res[4 * k + 1], res[4 * k + 2], res[4 * k + 3], sb + W_RES + wg * 10240 + k * 2048 + ta);
    }
    mbar_wait(BAR(qdone), 0);
    wg_wait<0>();
    TS(19);
#pragma unroll
    for (int i = 0; i < 20; i++) {
        const uint32_t y = pack2(aw[2 * i], aw[2 * i + 1]);
        asm("add.rn.bf16x2 %0, %0, %1;" : "+r"(res[i]) : "r"(y));
    }
#pragma unroll
    for (int k = 0; k < 5; k++) stsm_x4_t(sb + W_OUT + wg * 10240 + k * 2048 + ta, res[4 * k], res[4 * k + 1], res[4 * k + 2], res[4 * k + 3]);
    fence_async_smem();
    named_bar(1 + wg, 128);
    if (w == 0 && elect_one()) {
        asm volatile("cp.async.bulk.tensor.2d.global.shared::cta.bulk_group [%0, {%2, %3}], [%1];"
                     ::"l"(TMAP(6)), "r"(sb + W_OUT + wg * 10240), "r"(1024 * wg + 64 * blk), "r"(hg * 80) : "memory");
        bulk_commit();
    }
    __syncwarp();
    conv_tables();
    TS(20);
    {
        float sm[4] = {0.f, 0.f, 0.f, 0.f}, d0[4] = {0.f, 0.f, 0.f, 0.f}, d1[4] = {0.f, 0.f, 0.f, 0.f};
#pragma unroll
        for (int k = 0; k < 5; k++) {
            mma16816(sm, res[4 * k], res[4 * k + 1], res[4 * k + 2], res[4 * k + 3], 0x3F803F80u, 0x3F803F80u);
            mma16816(d0, res[4 * k], res[4 * k + 1], res[4 * k + 2], res[4 * k + 3], res[4 * k], res[4 * k + 2]);
            mma16816(d1, res[4 * k], res[4 * k + 1], res[4 * k + 2], res[4 * k + 3], res[4 * k + 1], res[4 * k + 3]);
        }
        const bool diag = q == (g >> 1);
        if (diag || q == ((g >> 1) ^ 1)) {
            float* dst = g_sums[layer][diag] + 1024 * wg + 64 * blk + 16 * w + g;
            asm volatile("red.global.add.f32 [%0], %1;" ::"l"(dst), "f"(diag ? ((g & 1) ? d0[1] : d0[0]) : sm[0]) : "memory");
            asm volatile("red.global.add.f32 [%0], %1;" ::"l"(dst + 8), "f"(diag ? ((g & 1) ? d1[3] : d1[2]) : sm[2]) : "memory");
        }
    }
    TS(21);
    named_bar(1 + wg, 128);
    asm volatile("setmaxnreg.dec.sync.aligned.u32 168;");
    TS(22);
    }
    TS_PHASE(2 * layer + 1);
    TS(0);
    indices();
    const int wg = warp >> 2;
    if (wg < npair) {
        conv_pair(2 * (pair0 + wg), layer, sb + F_EO + wg * 8192, sb + wg * Q_SB, sb + F_S23, BAR(kf), warp, lane, fa1, ftw, [&] {
            if (wg < 2 && (warp & 3) == 0 && elect_one()) { bulk_wait(); fence_async_global(); grid_arrive(g_bar[layer][hg]); }
            __syncwarp();
        }, [&] {
            if (warp == 0) {
                grid_wait(g_bar[layer][0], 8, 32 * (EPOCH + 1), lane);
                if (lane == 0) mbar_arrive(BAR(ardy));
            } else {
                mbar_wait(BAR(ardy), 0);
            }
        } TS_PASS);
        if (layer == 0) {
            named_bar(1 + wg, 128);
            if ((tid & 127) == 0) { mbar_arrive(BAR(fdone)); grid_arrive(g_bar[2][(pair0 + wg) >> 5]); }
            __syncwarp();
        }
    } else if (layer == 0 && warp == 8) {
        mbar_wait(BAR(ardy), 0);
        const long long t0 = clock64();
        while (clock64() - t0 < F_WDELAY) {}
        if (elect_one()) {
#pragma unroll 1
            for (int i = 0; i < 2 * Q_ST; i++) issue_w(BAR(full) + sizeof(Bars), i >> 1, i & 1);
        }
        __syncwarp();
    }
    if (wg >= npair) named_bar(3, 128);
    TS(20);
    }
    indices();
    __syncthreads();
    if (tid < 320) {
        const int cq = (warp & ~1) + (lane & 1), tg = 16 * (warp & 1) + (lane >> 1);
        const uint4* src = (const uint4*)&g_fin[40 * hg + 4 * cq][1024 * (tg >> 4) + 64 * blk + 4 * (tg & 15)];
        uint4 v[4];
#pragma unroll
        for (int i = 0; i < 4; i++) v[i].x = 0u;
        int spin = 0;
        while (true) {
#pragma unroll
            for (int i = 0; i < 4; i++) if (v[i].x == 0u) v[i] = ld_ll4(src + i * (FP / 4));
            if ((v[0].x && v[1].x && v[2].x && v[3].x) || ++spin >= (1 << 18)) break;
            __nanosleep(FIN_SLEEP);
        }
        TS(21);
        bf16* dst = out + (size_t)(128 * blk + 8 * (tg & 15) + (tg >> 4)) * DM + 80 * hg + 8 * cq;
#pragma unroll
        for (int i = 0; i < 4; i++) stg128(dst + 2 * i * DM, make_uint4(u4(v[0], i), u4(v[1], i), u4(v[2], i), u4(v[3], i)));
    }
    if (bx == 0 && tid == 0) g_epoch = EPOCH + 1;
    TS(22);
    TS_END;
}
typedef CUresult (*EncodeTiledFn)(CUtensorMap*, CUtensorMapDataType, cuuint32_t, void*, const cuuint64_t*, const cuuint64_t*, const cuuint32_t*,
                                  const cuuint32_t*, CUtensorMapInterleave, CUtensorMapSwizzle, CUtensorMapL2promotion, CUtensorMapFloatOOBfill);

static void make_map(EncodeTiledFn enc, CUtensorMap* m, const void* base, int rank, const cuuint64_t* dims, const cuuint64_t* strides,
                     const cuuint32_t* box, CUtensorMapSwizzle sw) {
    cuuint32_t es[4] = {1, 1, 1, 1};
    enc(m, CU_TENSOR_MAP_DATA_TYPE_BFLOAT16, rank, (void*)base, dims, strides, box, es, CU_TENSOR_MAP_INTERLEAVE_NONE, sw,
        sw == CU_TENSOR_MAP_SWIZZLE_128B ? CU_TENSOR_MAP_L2_PROMOTION_L2_128B : CU_TENSOR_MAP_L2_PROMOTION_NONE, CU_TENSOR_MAP_FLOAT_OOB_FILL_NONE);
}

template <typename... KArgs, typename... Args>
static void launch(void (*kern)(KArgs...), int grid, int block, int smem, int cluster, bool pdl, Args... args) {
    cudaLaunchConfig_t cfg = {};
    cfg.gridDim = dim3(grid); cfg.blockDim = dim3(block); cfg.dynamicSmemBytes = smem; cfg.stream = cudaStreamPerThread;
    cudaLaunchAttribute at[2];
    int n = 0;
    if (cluster > 1) { at[n].id = cudaLaunchAttributeClusterDimension; at[n].val.clusterDim.x = cluster; at[n].val.clusterDim.y = 1; at[n].val.clusterDim.z = 1; n++; }
    if (pdl) { at[n].id = cudaLaunchAttributeProgrammaticStreamSerialization; at[n].val.programmaticStreamSerializationAllowed = 1; n++; }
    cfg.attrs = at; cfg.numAttrs = n;
    cudaLaunchKernelEx(&cfg, kern, KArgs(args)...);
}

struct HostState {
    bool ready = false;
    const void* key[4] = {nullptr, nullptr, nullptr, nullptr};
    CUtensorMap mX[2], mRes[2], mW, mWr, mWo, mOut;
    bf16 *x1T, *x2T;
};

extern "C" void kernel_launch(void* const* d_in, const int* in_sizes, int n_in, void* d_out, int out_size) {
    const bf16* x = (const bf16*)d_in[0];
    const bf16* wqkv = (const bf16*)d_in[1];
    const bf16* wo = (const bf16*)d_in[2];
    const bf16* lar = (const bf16*)d_in[4];
    const bf16* aim = (const bf16*)d_in[5];
    const bf16* cre = (const bf16*)d_in[6];
    const bf16* cim = (const bf16*)d_in[7];
    const bf16* logdt = (const bf16*)d_in[8];
    const bf16* dskip = (const bf16*)d_in[9];
    static HostState hs;
    if (!hs.ready || hs.key[0] != wqkv || hs.key[1] != wo || hs.key[2] != x) {
        void* fn = nullptr;
        cudaDriverEntryPointQueryResult qr;
        cudaGetDriverEntryPoint("cuTensorMapEncodeTiled", &fn, cudaEnableDefault, &qr);
        EncodeTiledFn enc = (EncodeTiledFn)fn;
        cudaGetSymbolAddress((void**)&hs.x1T, g_x1T);
        cudaGetSymbolAddress((void**)&hs.x2T, g_x2T);
        {
            cuuint64_t d[3] = {DM, SEQ / 2, 2}, s[2] = {DM * 4, DM * 2};
            cuuint32_t b[3] = {64, 64, 2}, br[3] = {16, 64, 2};
            make_map(enc, &hs.mX[0], x, 3, d, s, b, CU_TENSOR_MAP_SWIZZLE_128B);
            make_map(enc, &hs.mRes[0], x, 3, d, s, br, CU_TENSOR_MAP_SWIZZLE_32B);
            cuuint64_t d2[3] = {SEQ / 2, DM, 2}, s2[2] = {XP * 2, SEQ};
            cuuint32_t b2[3] = {64, 80, 2};
            make_map(enc, &hs.mX[1], hs.x2T, 3, d2, s2, b, CU_TENSOR_MAP_SWIZZLE_128B);
            make_map(enc, &hs.mRes[1], hs.x2T, 3, d2, s2, b2, CU_TENSOR_MAP_SWIZZLE_128B);
            cuuint64_t d3[2] = {SEQ, DM};
            make_map(enc, &hs.mOut, hs.x1T, 2, d3, s2, b2, CU_TENSOR_MAP_SWIZZLE_128B);
        }
        { cuuint64_t d[2] = {3 * DM, DM}, s[1] = {3 * DM * 2}; cuuint32_t b[2] = {64, 32};
          make_map(enc, &hs.mW, wqkv, 2, d, s, b, CU_TENSOR_MAP_SWIZZLE_128B); }
        { cuuint64_t d[3] = {DM, DM, 3}, s[2] = {3 * DM * 2, DM * 2}; cuuint32_t b[3] = {16, 32, 3};
          make_map(enc, &hs.mWr, wqkv, 3, d, s, b, CU_TENSOR_MAP_SWIZZLE_32B); }
        { cuuint64_t d[4] = {8, 8, DM / 8, DM / 8}, s[3] = {DM * 2, 16, DM * 16}; cuuint32_t b[4] = {8, 8, 10, 5};
          make_map(enc, &hs.mWo, wo, 4, d, s, b, CU_TENSOR_MAP_SWIZZLE_NONE); }
        cudaFuncSetAttribute(fused_kernel, cudaFuncAttributeMaxDynamicSharedMemorySize, Q_SMEM);
        hs.key[0] = wqkv; hs.key[1] = wo; hs.key[2] = x;
        hs.ready = true;
    }
    const SsmParams sp = {lar, aim, cre, cim, logdt, dskip};
    launch(fused_kernel, 128, 384, Q_SMEM, 2, false, hs.mX[0], hs.mX[1], hs.mW, hs.mWr, hs.mRes[0], hs.mRes[1], hs.mOut, hs.mWo, (bf16*)d_out, sp);
}
```

```cpp
#include <cuda_runtime.h>
#include <cuda.h>
#include <cuda_bf16.h>
#include <cuda_fp16.h>
#include <stdint.h>

typedef __nv_bfloat16 bf16;

constexpr int SEQ = 2048;
constexpr int DM  = 640;
constexpr int XP  = SEQ + 64;
constexpr int NMODE = 192;

__device__ __forceinline__ uint32_t s2u(const void* p) { return (uint32_t)__cvta_generic_to_shared(p); }
__device__ __forceinline__ void mbar_init(uint32_t b, int c) { asm volatile("mbarrier.init.shared::cta.b64 [%0], %1;" ::"r"(b), "r"(c)); }
__device__ __forceinline__ void mbar_expect(uint32_t b, uint32_t bytes) { asm volatile("mbarrier.arrive.expect_tx.shared::cta.b64 _, [%0], %1;" ::"r"(b), "r"(bytes) : "memory"); }
__device__ __forceinline__ void mbar_arrive(uint32_t b) { asm volatile("mbarrier.arrive.shared::cta.b64 _, [%0];" ::"r"(b) : "memory"); }
__device__ __forceinline__ void mbar_arrive_cta(uint32_t b, uint32_t cta) {
    asm volatile("{\n.reg .b32 ra;\nmapa.shared::cluster.u32 ra, %0, %1;\nmbarrier.arrive.shared::cluster.b64 _, [ra];\n}" ::"r"(b), "r"(cta) : "memory");
}
__device__ __forceinline__ void mbar_wait(uint32_t b, uint32_t ph) {
    asm volatile("{\n.reg .pred p;\n.reg .u32 n;\nmbarrier.try_wait.parity.shared::cta.b64 p, [%0], %1;\n@p bra D;\nmov.u32 n, 0;\n"
                 "W: mbarrier.try_wait.parity.shared::cta.b64 p, [%0], %1;\n@p bra D;\nadd.u32 n, n, 1;\nsetp.lt.u32 p, n, 4194304;\n@p bra W;\ntrap;\nD:\n}"
                 ::"r"(b), "r"(ph) : "memory");
}
__device__ __forceinline__ void fence_mbar_init() { asm volatile("fence.mbarrier_init.release.cluster;" ::: "memory"); }
__device__ __forceinline__ void cluster_sync() { asm volatile("barrier.cluster.arrive.aligned;\nbarrier.cluster.wait.aligned;" ::: "memory"); }
__device__ __forceinline__ void pdl_wait() { asm volatile("griddepcontrol.wait;" ::: "memory"); }
__device__ __forceinline__ void pdl_launch() { asm volatile("griddepcontrol.launch_dependents;" ::: "memory"); }
__device__ __forceinline__ void named_bar(int id, int n) { asm volatile("bar.sync %0, %1;" ::"r"(id), "r"(n) : "memory"); }
__device__ __forceinline__ void fence_async_smem() { asm volatile("fence.proxy.async.shared::cta;" ::: "memory"); }

__device__ __forceinline__ void tma2d(uint32_t dst, const CUtensorMap* m, int c0, int c1, uint32_t bar) {
    asm volatile("cp.async.bulk.tensor.2d.shared::cluster.global.mbarrier::complete_tx::bytes [%0], [%1, {%3, %4}], [%2];"
                 ::"r"(dst), "l"(m), "r"(bar), "r"(c0), "r"(c1) : "memory");
}
__device__ __forceinline__ void tma2d_mc(uint32_t dst, const CUtensorMap* m, int c0, int c1, uint32_t bar, uint16_t mask) {
    asm volatile("cp.async.bulk.tensor.2d.shared::cluster.global.mbarrier::complete_tx::bytes.multicast::cluster [%0], [%1, {%3, %4}], [%2], %5;"
                 ::"r"(dst), "l"(m), "r"(bar), "r"(c0), "r"(c1), "h"(mask) : "memory");
}
__device__ __forceinline__ void tma3d(uint32_t dst, const CUtensorMap* m, int c0, int c1, int c2, uint32_t bar) {
    asm volatile("cp.async.bulk.tensor.3d.shared::cluster.global.mbarrier::complete_tx::bytes [%0], [%1, {%3, %4, %5}], [%2];"
                 ::"r"(dst), "l"(m), "r"(bar), "r"(c0), "r"(c1), "r"(c2) : "memory");
}
__device__ __forceinline__ void tma3d_mc(uint32_t dst, const CUtensorMap* m, int c0, int c1, int c2, uint32_t bar, uint16_t mask) {
    asm volatile("cp.async.bulk.tensor.3d.shared::cluster.global.mbarrier::complete_tx::bytes.multicast::cluster [%0], [%1, {%3, %4, %5}], [%2], %6;"
                 ::"r"(dst), "l"(m), "r"(bar), "r"(c0), "r"(c1), "r"(c2), "h"(mask) : "memory");
}
__device__ __forceinline__ void bulk_g2s(uint32_t dst, const void* src, uint32_t bytes, uint32_t bar) {
    asm volatile("cp.async.bulk.shared::cluster.global.mbarrier::complete_tx::bytes [%0], [%1], %2, [%3];"
                 ::"r"(dst), "l"(src), "r"(bytes), "r"(bar) : "memory");
}
__device__ __forceinline__ void bulk_g2s_mc(uint32_t dst, const void* src, uint32_t bytes, uint32_t bar, uint16_t mask) {
    asm volatile("cp.async.bulk.shared::cluster.global.mbarrier::complete_tx::bytes.multicast::cluster [%0], [%1], %2, [%3], %4;"
                 ::"r"(dst), "l"(src), "r"(bytes), "r"(bar), "h"(mask) : "memory");
}
__device__ __forceinline__ void prefetch_l2(const void* p, uint32_t bytes) { asm volatile("cp.async.bulk.prefetch.L2.global [%0], %1;" ::"l"(p), "r"(bytes) : "memory"); }
__device__ __forceinline__ void prefetch_tmap(const CUtensorMap* m) { asm volatile("prefetch.tensormap [%0];" ::"l"(m) : "memory"); }

__device__ __forceinline__ void wg_fence() { asm volatile("wgmma.fence.sync.aligned;" ::: "memory"); }
__device__ __forceinline__ void wg_commit() { asm volatile("wgmma.commit_group.sync.aligned;" ::: "memory"); }
template <int N> __device__ __forceinline__ void wg_wait() { asm volatile("wgmma.wait_group.sync.aligned %0;" ::"n"(N) : "memory"); }
__device__ __forceinline__ uint64_t mkdesc(uint32_t addr, uint32_t lbo, uint32_t sbo, uint32_t mode) {
    return (uint64_t)((addr & 0x3FFFF) >> 4) | ((uint64_t)(lbo >> 4) << 16) | ((uint64_t)(sbo >> 4) << 32) | ((uint64_t)mode << 62);
}

__device__ __forceinline__ void mma16816(float (&c)[4], uint32_t a0, uint32_t a1, uint32_t a2, uint32_t a3, uint32_t b0, uint32_t b1) {
    asm("mma.sync.aligned.m16n8k16.row.col.f32.bf16.bf16.f32 {%0,%1,%2,%3},{%4,%5,%6,%7},{%8,%9},{%0,%1,%2,%3};"
                 : "+f"(c[0]), "+f"(c[1]), "+f"(c[2]), "+f"(c[3]) : "r"(a0), "r"(a1), "r"(a2), "r"(a3), "r"(b0), "r"(b1));
}
__device__ __forceinline__ void mma1688(float (&c)[4], uint32_t a0, uint32_t a1, uint32_t b0) {
    asm("mma.sync.aligned.m16n8k8.row.col.f32.bf16.bf16.f32 {%0,%1,%2,%3},{%4,%5},{%6},{%0,%1,%2,%3};"
                 : "+f"(c[0]), "+f"(c[1]), "+f"(c[2]), "+f"(c[3]) : "r"(a0), "r"(a1), "r"(b0));
}
__device__ __forceinline__ void ldsm_x4(uint32_t& r0, uint32_t& r1, uint32_t& r2, uint32_t& r3, uint32_t a) {
    asm volatile("ldmatrix.sync.aligned.m8n8.x4.shared.b16 {%0,%1,%2,%3}, [%4];" : "=r"(r0), "=r"(r1), "=r"(r2), "=r"(r3) : "r"(a) : "memory");
}
__device__ __forceinline__ void ldsm_x4_t(uint32_t& r0, uint32_t& r1, uint32_t& r2, uint32_t& r3, uint32_t a) {
    asm volatile("ldmatrix.sync.aligned.m8n8.x4.trans.shared.b16 {%0,%1,%2,%3}, [%4];" : "=r"(r0), "=r"(r1), "=r"(r2), "=r"(r3) : "r"(a) : "memory");
}
__device__ __forceinline__ void ldsm_x2(uint32_t& r0, uint32_t& r1, uint32_t a) {
    asm volatile("ldmatrix.sync.aligned.m8n8.x2.shared.b16 {%0,%1}, [%2];" : "=r"(r0), "=r"(r1) : "r"(a) : "memory");
}
__device__ __forceinline__ void ldsm_x2_t(uint32_t& r0, uint32_t& r1, uint32_t a) {
    asm volatile("ldmatrix.sync.aligned.m8n8.x2.trans.shared.b16 {%0,%1}, [%2];" : "=r"(r0), "=r"(r1) : "r"(a) : "memory");
}
__device__ __forceinline__ void stsm_x4(uint32_t a, uint32_t r0, uint32_t r1, uint32_t r2, uint32_t r3) {
    asm volatile("stmatrix.sync.aligned.m8n8.x4.shared.b16 [%0], {%1,%2,%3,%4};" ::"r"(a), "r"(r0), "r"(r1), "r"(r2), "r"(r3) : "memory");
}
__device__ __forceinline__ void stsm_x4_t(uint32_t a, uint32_t r0, uint32_t r1, uint32_t r2, uint32_t r3) {
    asm volatile("stmatrix.sync.aligned.m8n8.x4.trans.shared.b16 [%0], {%1,%2,%3,%4};" ::"r"(a), "r"(r0), "r"(r1), "r"(r2), "r"(r3) : "memory");
}
__device__ __forceinline__ void stsm_x2(uint32_t a, uint32_t r0, uint32_t r1) {
    asm volatile("stmatrix.sync.aligned.m8n8.x2.shared.b16 [%0], {%1,%2};" ::"r"(a), "r"(r0), "r"(r1) : "memory");
}
__device__ __forceinline__ uint32_t movm_t(uint32_t a) {
    uint32_t d;
    asm volatile("movmatrix.sync.aligned.m8n8.trans.b16 %0, %1;" : "=r"(d) : "r"(a));
    return d;
}
__device__ __forceinline__ uint32_t lds32(uint32_t a) { uint32_t v; asm volatile("ld.shared.u32 %0, [%1];" : "=r"(v) : "r"(a) : "memory"); return v; }
__device__ __forceinline__ uint32_t ldsv32(uint32_t a) { uint32_t v; asm volatile("ld.volatile.shared.u32 %0, [%1];" : "=r"(v) : "r"(a) : "memory"); return v; }
__device__ __forceinline__ void sts32(uint32_t a, uint32_t v) { asm volatile("st.shared.u32 [%0], %1;" ::"r"(a), "r"(v) : "memory"); }
__device__ __forceinline__ uint4 lds128(uint32_t a) { uint4 v; asm volatile("ld.shared.v4.u32 {%0,%1,%2,%3}, [%4];" : "=r"(v.x), "=r"(v.y), "=r"(v.z), "=r"(v.w) : "r"(a) : "memory"); return v; }
__device__ __forceinline__ void sts128(uint32_t a, uint4 v) { asm volatile("st.shared.v4.u32 [%0], {%1,%2,%3,%4};" ::"r"(a), "r"(v.x), "r"(v.y), "r"(v.z), "r"(v.w) : "memory"); }

__device__ __forceinline__ void stg128(void* p, uint4 v) { asm volatile("st.global.v4.u32 [%0], {%1,%2,%3,%4};" ::"l"(p), "r"(v.x), "r"(v.y), "r"(v.z), "r"(v.w) : "memory"); }

__device__ __forceinline__ uint4 ldg128(const void* p) { uint4 v; asm volatile("ld.global.v4.u32 {%0,%1,%2,%3}, [%4];" : "=r"(v.x), "=r"(v.y), "=r"(v.z), "=r"(v.w) : "l"(p) : "memory"); return v; }
__device__ __forceinline__ uint2 ldg64(const void* p) { uint2 v; asm volatile("ld.global.v2.u32 {%0,%1}, [%2];" : "=r"(v.x), "=r"(v.y) : "l"(p) : "memory"); return v; }
__device__ __forceinline__ uint32_t ldg32(const void* p) { uint32_t v; asm volatile("ld.global.u32 %0, [%1];" : "=r"(v) : "l"(p) : "memory"); return v; }

__device__ __forceinline__ uint32_t pack2(float lo, float hi) {
    uint32_t r;
    asm("cvt.rn.bf16x2.f32 %0, %1, %2;" : "=r"(r) : "f"(hi), "f"(lo));
    return r;
}
__device__ __forceinline__ float bf_lo(uint32_t v) { return __uint_as_float(v << 16); }
__device__ __forceinline__ float bf_hi(uint32_t v) { return __uint_as_float(v & 0xFFFF0000u); }
__device__ __forceinline__ float rbf(float x) { return __uint_as_float(pack2(0.f, x) & 0xFFFF0000u); }
__device__ __forceinline__ float ex2(float x) { float r; asm("ex2.approx.ftz.f32 %0, %1;" : "=f"(r) : "f"(x)); return r; }

__device__ __forceinline__ float2 ln_finish(float sum, float sumsq) {
    const float m = sum * (1.0f / DM);
    const float v = fmaxf(fmaf(sumsq, 1.0f / DM, -m * m), 0.f);
    float s, r;
    asm("sqrt.approx.ftz.f32 %0, %1;" : "=f"(s) : "f"(rbf(rbf(v) + 1e-5f)));
    asm("rcp.approx.ftz.f32 %0, %1;" : "=f"(r) : "f"(rbf(s)));
    return make_float2(m, r);
}
__device__ __forceinline__ uint32_t ln_finish_packed(float sum, float sumsq) {
    const float m = sum * (1.0f / DM);
    const float v = fmaxf(fmaf(sumsq, 1.0f / DM, -m * m), 0.f);
    float s;
    asm("sqrt.approx.ftz.f32 %0, %1;" : "=f"(s) : "f"(rbf(rbf(v) + 1e-5f)));
    return pack2(s, m);
}
__device__ __forceinline__ float frsq(float x) { float r; asm("rsqrt.approx.ftz.f32 %0, %1;" : "=f"(r) : "f"(x)); return r; }
__device__ __forceinline__ float frcp(float x) { float r; asm("rcp.approx.ftz.f32 %0, %1;" : "=f"(r) : "f"(x)); return r; }
__device__ __forceinline__ bool elect_one() {
    uint32_t p;
    asm volatile("{\n.reg .pred p;\nelect.sync _|p, 0xffffffff;\nselp.u32 %0, 1, 0, p;\n}" : "=r"(p));
    return p != 0;
}
__device__ __forceinline__ void cluster_arrive_relaxed() { asm volatile("barrier.cluster.arrive.relaxed.aligned;" ::: "memory"); }
__device__ __forceinline__ void cluster_wait() { asm volatile("barrier.cluster.wait.aligned;" ::: "memory"); }
__device__ __forceinline__ unsigned long long ld_ll(const unsigned long long* p) {
    unsigned long long v;
    asm volatile("ld.relaxed.gpu.global.b64 %0, [%1];" : "=l"(v) : "l"(p) : "memory");
    return v;
}
__device__ __forceinline__ void st_ll(unsigned long long* p, uint32_t payload, uint32_t tag) {
    const unsigned long long v = (unsigned long long)payload | ((unsigned long long)tag << 32);
    asm volatile("st.relaxed.gpu.global.b64 [%0], %1;" ::"l"(p), "l"(v) : "memory");
}
__device__ __forceinline__ uint4 ld_ll4(const uint4* p) {
    uint4 v;
    asm volatile("{\n.reg .b128 t;\n.reg .b64 a, b;\nld.relaxed.gpu.global.b128 t, [%4];\nmov.b128 {a, b}, t;\nmov.b64 {%0, %1}, a;\nmov.b64 {%2, %3}, b;\n}"
                 : "=r"(v.x), "=r"(v.y), "=r"(v.z), "=r"(v.w) : "l"(p) : "memory");
    return v;
}
__device__ __forceinline__ void st_ll4(uint4* p, uint32_t x, uint32_t y, uint32_t z, uint32_t w) {
    asm volatile("{\n.reg .b128 t;\n.reg .b64 a, b;\nmov.b64 a, {%1, %2};\nmov.b64 b, {%3, %4};\nmov.b128 t, {a, b};\nst.relaxed.gpu.global.b128 [%0], t;\n}"
                 ::"l"(p), "r"(x), "r"(y), "r"(z), "r"(w) : "memory");
}

__device__ __forceinline__ void bulk_s2g(void* dst, uint32_t src, uint32_t bytes) {
    asm volatile("cp.async.bulk.global.shared::cta.bulk_group [%0], [%1], %2;" ::"l"(dst), "r"(src), "r"(bytes) : "memory");
}
__device__ __forceinline__ void bulk_commit() { asm volatile("cp.async.bulk.commit_group;" ::: "memory"); }
__device__ __forceinline__ void bulk_wait() { asm volatile("cp.async.bulk.wait_group 0;" ::: "memory"); }
__device__ __forceinline__ void fence_async_global() { asm volatile("fence.proxy.async.global;" ::: "memory"); }
__device__ __forceinline__ void fence_release() { asm volatile("fence.release.gpu;" ::: "memory"); }
__device__ __forceinline__ void fence_acquire() { asm volatile("fence.acquire.gpu;" ::: "memory"); }
template<int TA, int TB>
__device__ __forceinline__ void wgmma_n192(float (&d)[96], uint64_t da, uint64_t db, int scale_d) {
  asm volatile("{\n.reg .pred p;\nsetp.ne.b32 p, %98, 0;\n"
    "wgmma.mma_async.sync.aligned.m64n192k16.f32.bf16.bf16 "
    "{%0, %1, %2, %3, %4, %5, %6, %7, %8, %9, %10, %11, %12, %13, %14, %15, %16, %17, %18, %19, %20, %21, %22, %23, %24, %25, %26, %27, %28, %29, %30, %31, %32, %33, %34, %35, %36, %37, %38, %39, %40, %41, %42, %43, %44, %45, %46, %47, %48, %49, %50, %51, %52, %53, %54, %55, %56, %57, %58, %59, %60, %61, %62, %63, %64, %65, %66, %67, %68, %69, %70, %71, %72, %73, %74, %75, %76, %77, %78, %79, %80, %81, %82, %83, %84, %85, %86, %87, %88, %89, %90, %91, %92, %93, %94, %95}, %96, %97, p, 1, 1, %99, %100;\n}\n"
    : "+f"(d[0]), "+f"(d[1]), "+f"(d[2]), "+f"(d[3]), "+f"(d[4]), "+f"(d[5]), "+f"(d[6]), "+f"(d[7]), "+f"(d[8]), "+f"(d[9]), "+f"(d[10]), "+f"(d[11]), "+f"(d[12]), "+f"(d[13]), "+f"(d[14]), "+f"(d[15]), "+f"(d[16]), "+f"(d[17]), "+f"(d[18]), "+f"(d[19]), "+f"(d[20]), "+f"(d[21]), "+f"(d[22]), "+f"(d[23]), "+f"(d[24]), "+f"(d[25]), "+f"(d[26]), "+f"(d[27]), "+f"(d[28]), "+f"(d[29]), "+f"(d[30]), "+f"(d[31]), "+f"(d[32]), "+f"(d[33]), "+f"(d[34]), "+f"(d[35]), "+f"(d[36]), "+f"(d[37]), "+f"(d[38]), "+f"(d[39]), "+f"(d[40]), "+f"(d[41]), "+f"(d[42]), "+f"(d[43]), "+f"(d[44]), "+f"(d[45]), "+f"(d[46]), "+f"(d[47]), "+f"(d[48]), "+f"(d[49]), "+f"(d[50]), "+f"(d[51]), "+f"(d[52]), "+f"(d[53]), "+f"(d[54]), "+f"(d[55]), "+f"(d[56]), "+f"(d[57]), "+f"(d[58]), "+f"(d[59]), "+f"(d[60]), "+f"(d[61]), "+f"(d[62]), "+f"(d[63]), "+f"(d[64]), "+f"(d[65]), "+f"(d[66]), "+f"(d[67]), "+f"(d[68]), "+f"(d[69]), "+f"(d[70]), "+f"(d[71]), "+f"(d[72]), "+f"(d[73]), "+f"(d[74]), "+f"(d[75]), "+f"(d[76]), "+f"(d[77]), "+f"(d[78]), "+f"(d[79]), "+f"(d[80]), "+f"(d[81]), "+f"(d[82]), "+f"(d[83]), "+f"(d[84]), "+f"(d[85]), "+f"(d[86]), "+f"(d[87]), "+f"(d[88]), "+f"(d[89]), "+f"(d[90]), "+f"(d[91]), "+f"(d[92]), "+f"(d[93]), "+f"(d[94]), "+f"(d[95])
    : "l"(da), "l"(db), "r"(scale_d), "n"(TA), "n"(TB));
}

template<int TA, int TB>
__device__ __forceinline__ void wgmma_n48(float (&d)[24], uint64_t da, uint64_t db, int scale_d) {
  asm volatile("{\n.reg .pred p;\nsetp.ne.b32 p, %26, 0;\n"
    "wgmma.mma_async.sync.aligned.m64n48k16.f32.bf16.bf16 "
    "{%0, %1, %2, %3, %4, %5, %6, %7, %8, %9, %10, %11, %12, %13, %14, %15, %16, %17, %18, %19, %20, %21, %22, %23}, %24, %25, p, 1, 1, %27, %28;\n}\n"
    : "+f"(d[0]), "+f"(d[1]), "+f"(d[2]), "+f"(d[3]), "+f"(d[4]), "+f"(d[5]), "+f"(d[6]), "+f"(d[7]), "+f"(d[8]), "+f"(d[9]), "+f"(d[10]), "+f"(d[11]), "+f"(d[12]), "+f"(d[13]), "+f"(d[14]), "+f"(d[15]), "+f"(d[16]), "+f"(d[17]), "+f"(d[18]), "+f"(d[19]), "+f"(d[20]), "+f"(d[21]), "+f"(d[22]), "+f"(d[23])
    : "l"(da), "l"(db), "r"(scale_d), "n"(TA), "n"(TB));
}

__device__ __forceinline__ void wgmma_rs80(float (&d)[40], const uint4& a, uint64_t db, int scale_d) {
  asm volatile("{\n.reg .pred p;\nsetp.ne.b32 p, %45, 0;\n"
    "wgmma.mma_async.sync.aligned.m64n80k16.f32.bf16.bf16 {%0,%1,%2,%3,%4,%5,%6,%7,%8,%9,%10,%11,%12,%13,%14,%15,%16,%17,%18,%19,%20,%21,%22,%23,%24,%25,%26,%27,%28,%29,%30,%31,%32,%33,%34,%35,%36,%37,%38,%39}, {%40,%41,%42,%43}, %44, p, 1, 1, 1;\n}\n"
    : "+f"(d[0]), "+f"(d[1]), "+f"(d[2]), "+f"(d[3]), "+f"(d[4]), "+f"(d[5]), "+f"(d[6]), "+f"(d[7]), "+f"(d[8]), "+f"(d[9]), "+f"(d[10]), "+f"(d[11]), "+f"(d[12]), "+f"(d[13]), "+f"(d[14]), "+f"(d[15]), "+f"(d[16]), "+f"(d[17]), "+f"(d[18]), "+f"(d[19]), "+f"(d[20]), "+f"(d[21]), "+f"(d[22]), "+f"(d[23]), "+f"(d[24]), "+f"(d[25]), "+f"(d[26]), "+f"(d[27]), "+f"(d[28]), "+f"(d[29]), "+f"(d[30]), "+f"(d[31]), "+f"(d[32]), "+f"(d[33]), "+f"(d[34]), "+f"(d[35]), "+f"(d[36]), "+f"(d[37]), "+f"(d[38]), "+f"(d[39])
    : "r"(a.x), "r"(a.y), "r"(a.z), "r"(a.w), "l"(db), "r"(scale_d));
}

__device__ const __align__(1024) uint32_t c_fft[11264] = {
0x2ddc2dba,0x2fe62eb5,0x2ed02eb5,0xafffaf6e,0x2e1f2dfe,0x2e3f2fbc,0x2f022ee9,0xad27af30,0x2e5e2e3f,0x1fd92b5e,0x2f302f1a,0x244ea875,0x2e992e7c,0xad96a993,0x2f5a2f46,0x2e992c32,
0xad00ad72,0xa17eac32,0xa17ea515,0xabb79cb6,0xac07ac87,0x2dfe29f1,0x1fd99648,0xafedae99,0xa9f1ab05,0x2fd42fbc,0x26a1244e,0xad96af91,0xa765a8d5,0x2aaa2e3f,0x29932875,0x2515a8d5,
0xae99adfe,0xb000aee9,0xaf6eafbc,0x2c872f30,0xaf80af1a,0xac32af02,0xae7caf02,0xaaaa217e,0xaff4afc9,0x2b5e9cb6,0xad27addc,0xaff4ae7c,0xafedb000,0x2ffc2eb5,0xab05ac5d,0xacd8af5a,
0x2c072d27,0x9fd92bb7,0xadfead00,0x2fed2e1f,0x25db2993,0xaf6eacb0,0xaf6eaed0,0x2c5d2f46,0xa5151648,0xaddcafdd,0xafffafd4,0xac321648,0xabb7a934,0x28d5a814,0xafa0afed,0xaff4af30,
0x2f302e3f,0x2fed2f1a,0x28142b5e,0x2934a875,0x30002fc9,0x26a12ddc,0xa5db1cb6,0x30002e7c,0x2f462fd4,0xaed0aa4e,0xacb0aa4e,0x29932e99,0x2d272e5e,0xae3faffc,0xaf02adfe,0xae1fa814,
0xa9f1acd8,0x26a1ab05,0x2fd42ffc,0xad96afed,0x2515a30e,0x2fff2e1f,0x2ddc2f1a,0x2c32a30e,0x2d272aaa,0x28752e7c,0x28752c32,0x2fa02f80,0x2f912e99,0xaee9a9f1,0xa8141648,0x9fd92c87,
0xafa0ae7c,0xafafaf46,0x2d002993,0xafa0ac32,0xaf91b000,0x244eac5d,0x2fbc2eb5,0xab05af5a,0xac87ae5e,0x30002dfe,0x2f6e2ffc,0x2e992814,0x1cb6a875,0x25152e1f,0x2c322e1f,0x2d722ff4,
0x27652c87,0xa9932a4e,0xaaaaadba,0xa5152c87,0xabb7a44e,0xafa0af30,0x28d59fd9,0xaff4ae5e,0xaf91ae1f,0x2814abb7,0x2ee92d00,0x1fd9ad27,0xaf5aafff,0x2fd42ed0,0x2fd42fe6,0x30002ddc,
0x2f462f6e,0x2c322fdd,0x2e7c2fdd,0xa993b000,0xab5e2934,0xafafacd8,0xad00244e,0x2f1a2dfe,0xaee9afaf,0x2f30a17e,0xadfeaff8,0xafbca30e,0x2c5da765,0xa9f12ddc,0x2d969cb6,0x2c5dacb0,
0x2bb7a993,0x2f1aa515,0x2f1a2765,0xaff4aaaa,0x2e5e2fd4,0xab052dba,0x29342f6e,0x2ee9a6a1,0xadba1fd9,0xa5dbafed,0xafddac07,0xaa4e2dfe,0xacb0aff8,0x2ddc2f02,0x9cb6ae3f,0xa765aff8,
0xaeb5af91,0xaa4eafed,0x9648ae5e,0xac5d2d4d,0x2ddca17e,0x2e7c2e3f,0x2fc92e3f,0x1cb6afa0,0x2bb72fe6,0xaff8a993,0xab5e2aaa,0x2bb72fc9,0xafbcaa4e,0x2f30a5db,0xadfeafdd,0xaee9adba,
0xacd828d5,0xaf91230e,0xaf30af02,0x2c072fa0,0xac5dafff,0x2dbaac32,0x2dbaa515,0xae99addc,0x2fc929f1,0xa9932eb5,0x2aaa2fdd,0x2fe629f1,0xa30e2dfe,0xa17eafed,0xaff8ac07,0xafaf1fd9,
0x2dfe2faf,0x28142ff8,0xae5e217e,0x2ffc230e,0xaf5aa515,0xac87af46,0xa6a1af80,0xaf5a2765,0x1cb6ae99,0x2e7c2dba,0x2fc92dba,0x2ddcac5d,0x2f1a2ee9,0xafafab05,0xad002934,0xab5e2e5e,
0x2dbaa814,0x2fdd9fd9,0x25db2f91,0x2a4eaee9,0x27652faf,0xaf4628d5,0xaf80ae1f,0xa5152faf,0xafa0addc,0x2e3fac32,0x2e3fa515,0xa17eafff,0x2dfea6a1,0xacd82dba,0x244e2f6e,0x29342fd4,
0xad27afc9,0xa30eafff,0x2faf2d72,0xad27ae7c,0x2ffc2a4e,0x28142fdd,0xae5e25db,0x2dfe2dba,0xac5d2c07,0xaa4eaf91,0x9648af30,0xaeb5acd8,0xa993aff4,0x2c322f1a,0x2e7c2f1a,0x2f462bb7,
0xae7c26a1,0xafff1648,0x2d72aa4e,0xafc926a1,0x230eaee9,0x2ff89fd9,0x217e2f91,0x2fafa814,0x2d4d2fa0,0xafed230e,0xae5eaf02,0xaf9128d5,0xb000aaaa,0x2fdda515,0x2fdd2765,0x2f6ea993,
0x9cb63000,0xacb02fd4,0xa7652fd4,0x2ddcaf5a,0x217eaffc,0x2ff4ac07,0x2875afbc,0xaff82934,0xa44e2ff4,0xadfea8d5,0xa9342fa0,0x2cd82bb7,0x25dbafe6,0x16482f46,0x29f1af80,0x25dbafc9,
0x2ff41cb6,0x2e1f2765,0x2e1f2cb0,0xa875addc,0xafbca5db,0x1fd9af5a,0xad4dad96,0xacd82fdd,0x2f5a2934,0xaeb52ee9,0x2c5d2e5e,0x3000ab05,0xaed0ab5e,0x2f80a30e,0xaaaaaf02,0xacb0ab5e,
0x25dbaffc,0x2d96afbc,0x2f5aac07,0xafdd2934,0xaaaa2fa0,0xafc92875,0xafe62875,0x29932d27,0x2d00aed0,0x28d52d72,0x2ff89cb6,0x2d00afe6,0xae5e2d96,0x2d4dafd4,0xaf91a6a1,0xafed29f1,
0xafbca17e,0xad4da875,0x1fd9aff4,0xacd82ff8,0x2e992aaa,0xaa4e2fe6,0xaa4e2fc9,0x2fd4a993,0xacb0ad96,0x2fffac87,0x2d72aeb5,0xa765ad96,0x28752f30,0xab5eac07,0xaf1a2cd8,0xae3f2f91,
0xa9342ff4,0xae5e2fa0,0xaee9a8d5,0x2b052bb7,0x2d96aed0,0x2eb59cb6,0x2c872d72,0x2d96afe6,0xaf802c5d,0x2765af6e,0xa515af6e,0xaf4625db,0x2ff8a44e,0xaff42d4d,0xa8752ffc,0xa17e2ee9,
0x2f5a244e,0x2c5d2934,0xaeb52dfe,0x3000acd8,0xacb0ad00,0x2d72aff8,0x2fffa8d5,0xa765ad00,0x217e2f80,0xaf022515,0xaf02a765,0xaf1a2f46,0x2b05afdd,0xa8142f5a,0x2c072d96,0x2d4d25db,
0x2b5eafe6,0x2f02af80,0x230e2f46,0x2b5eafc9,0xaf302d96,0xacd8a6a1,0x2c07afd4,0xaf9129f1,0x2fdda44e,0xad962ffc,0xaf5a2d4d,0xa5db2ee9,0xad72abb7,0x2e7ca17e,0x2fc9a17e,0x2fffad00,
0xaed0a5db,0xaaaaa9f1,0x2f809648,0xacb0a5db,0x28752e5e,0xaf1a2f91,0xab5ead4d,0xae3f2fed,0x2b05aff8,0x2c072875,0xa8142ff4,0x2d4d217e,0xaf6e2d72,0x2eb5afc9,0x2eb5ae7c,0x2dbaafff,
0xaf802f5a,0xafc92e99,0xafe62e99,0x2f46ad96,0x28d52b05,0xaf022fed,0x230e2cd8,0x2fa0affc,0x2fbcaf02,0xa9342d27,0x2ffcae1f,0x2c07ae3f,0xa6a1ac32,0x2a4e9cb6,0x9648ad72,0xa6a1a515,
0x28752aaa,0xa8d52cb0,0xa8d52ed0,0x2e3faf80,0x2fedaeb5,0x29349648,0x2f30aa4e,0x2814ac5d,0x1648ad4d,0x2e99acd8,0x2c87afbc,0xa9f11fd9,0xafe62d27,0x2fffafaf,0xaddc230e,0xaed02d27,
0x2fd4af30,0x2f6eae5e,0x2dbaa44e,0xa6a19fd9,0x1cb6ad27,0x2fe6aff4,0x2ed0aff4,0xad722b5e,0xafaf2cb0,0x2e1faf46,0xa8d5a993,0xafaf2ed0,0xac072f6e,0x2934ac87,0xaffc2e99,0xafbc3000,
0xa44eab5e,0x2b05ad00,0x2f91afaf,0xafbc2f1a,0xafd42d72,0x1648a765,0x1648acb0,0xafdd2fff,0xac322f5a,0xaaaa26a1,0xaf802c87,0xae7c2f5a,0x2d009fd9,0xae1f2cd8,0xad272fbc,0xabb72d4d,
0xaffc2f02,0xaee92e1f,0x244ead27,0xad4d2e3f,0xa9f12e7c,0xafdd2f80,0xaeb52aaa,0xa9f12c32,0x2d72a5db,0xafe63000,0xaed03000,0x9cb626a1,0x2fa0afbc,0xaf022f91,0x230e2b05,0x28d5a44e,
0x96482c07,0xac872d4d,0xae992b05,0x29f1a814,0x2ed0abb7,0xa9932b5e,0xaf462ff8,0x2cb0abb7,0x2f1aafff,0xa30e2765,0xa30e2cb0,0x2e1fad72,0x1fd9ac5d,0x244e9648,0x2e5eaa4e,0x2f30aeb5,
0x2ff8aed0,0x2e3faddc,0xaf022fff,0x2ff8afe6,0x2d4daf6e,0x2ee9ae99,0xa44e2c87,0x2ffcb000,0xa6a1a814,0x2f6eaf30,0x2dbaa934,0x2fd4afed,0xaf462d00,0x2fc9afa0,0x2fe6afa0,0x2f80afaf,
0x2515ac5d,0x2d72ad96,0x1cb629f1,0x2c32ac5d,0xad002814,0x2d27ad4d,0x2e1fab05,0x2bb7ac07,0xaffc2f1a,0x2cd8ad00,0x2fedafaf,0x2b05ab5e,0xadba2f80,0x2c87acb0,0x2c87aed0,0x2a4eaaaa,
0x2f802f6e,0x2fc92fdd,0x2fe62fdd,0xaf46b000,0x2fa02f91,0x2bb72e5e,0x2ff42fed,0xa8d5ad4d,0x2fbc2faf,0xa934217e,0x2ffc2ff8,0x2c07230e,0x2fd42fc9,0xaf5aad72,0x30002fff,0x2fd42e7c,
0x2bb72aaa,0x2f1a2cb0,0x2f1a2ed0,0xaff4af80,0x2cd82c5d,0x2f303000,0x2f912f5a,0xac07aeb5,0x2dba2d4d,0x25db2cd8,0x2fdd2fbc,0x2a4e9fd9,0x2e7c2e1f,0xad72a875,0x2fff2ff4,0x2fc92e1f,
0xa6a1a934,0x29f1a44e,0x2d962cd8,0xafd4adfe,0x1cb6a17e,0x2fe62e3f,0x2ed02e3f,0xad72afa0,0x28752515,0x2d272f80,0x2fa02f46,0x2875a765,0x2c072a4e,0xa93425db,0x2ffc2fdd,0x2fbc2dba,
0xae5eaf1a,0xa934ae3f,0x2b052875,0xaee9ab5e,0xac5dad72,0x2dba2765,0x2dba2cb0,0xae99afff,0xa765aa4e,0x2f802fd4,0x2f462e99,0x2515aa4e,0x230e9fd9,0x217e2cd8,0x2ff82fbc,0x2faf2d4d,
0xaffcafaf,0xaee9aff8,0x244ea17e,0xad4da30e,0xaf6eafe6,0x25dbaaaa,0x2c5d2993,0xaf6eafc9,0xad72ae99,0x2fe62dba,0x2ed02dba,0x1cb6ac5d,0xa8d5ac07,0x2bb72f30,0x2ff42f91,0x2fa02cd8,
0xadbaac07,0xafddad4d,0xa5dbab05,0xaa4e2814,0xafc9af02,0xaaaaaf1a,0x2993217e,0xafe6af02,0xafa0afff,0x2e3f2765,0x2e3f2cb0,0xa17ead72,0xad4daeb5,0x2e5e3000,0x2fed2f5a,0x2f912c5d,
0xa17e2765,0xad001cb6,0xabb7addc,0xa17e2cb0,0xad4daa4e,0xaee9afdd,0x244ea5db,0xaffcadba,0xafd4aee9,0x29f1a934,0x2d962b05,0xa6a1ae5e,0xaf46aff4,0x2fc92f1a,0x2fe62f1a,0x2f802bb7,
0x2cb02eb5,0x1cb62dba,0xaddcaf6e,0x27652eb5,0xa30e2814,0xaff8ad4d,0xa17eab05,0xafafac07,0xadfeab5e,0xa44eae3f,0x2cd82875,0xa934af1a,0xb000af80,0x2fdd2cb0,0x2fdd2ed0,0x2f6e2aaa,
0x2d723000,0x25152fd4,0x2c322fd4,0x1cb6af5a,0xae1f9fd9,0xae3faee9,0xaf02a814,0x2d272f91,0xacd8aff4,0x2ffc28d5,0xab05afa0,0xafedabb7,0x2e992515,0xad962aaa,0x2f5a2993,0x2e99a765,
0x2ff42ddc,0x2e1f2ed0,0x2e1f2fe6,0xa875afff,0xa8142c87,0xaffca9f1,0xadfe1648,0x2e5e2e99,0xaf5aaf30,0x2eb5a814,0xac5dafed,0xb000a934,0x2c32a8d5,0xa9932e3f,0x2f462875,0x2e7ca8d5,
0x2e991fd9,0x30002814,0x2f6e2ee9,0xac87af91,0x29932fa0,0xaed02875,0xacb02875,0x2f462d27,0xaff4ac32,0x2b5eaddc,0xad27afff,0xaff4a515,0x244ead96,0x1fd92fd4,0x2f3026a1,0x2e5ea9f1,
0x2814ad27,0x2dfeabb7,0x2ffc2d00,0xae5eae1f,0x2e992f80,0xaa4e2e7c,0xaa4e2c32,0x2fd42aaa,0xae7c1648,0x9cb6afdd,0xaddcafd4,0xafc91648,0xa875af91,0x2b5e2fbc,0x2f1a244e,0x2e3fab05,
0xab05aff4,0x244eafa0,0x2fbc28d5,0xaf91abb7,0x30002c32,0x26a12fff,0xa5db2ddc,0x30002515,0xaaaa2c5d,0xac32af6e,0xae7caf6e,0xaf8025db,0xad27afed,0x2e3f2dfe,0x2f021fd9,0x2e1fac07,
0xaf5aae5e,0xac5daf30,0x2eb59fd9,0xb000a44e,0x2e7ca30e,0x2ddc2e1f,0x1cb62f1a,0x2fc9a30e,0x217e2f46,0xaf02acb0,0xaf02aed0,0xaf1a2993,0xaf30ae99,0x2fbc29f1,0x2ee99648,0x2dfeac87,
0xafa0a515,0xafafa993,0x2d00aaaa,0xafa02765,0x2934ad96,0x2fed26a1,0x28142fd4,0x2f30a9f1,0x2c872fed,0xb0009fd9,0xaf6eadfe,0xae992c07,0xafffabb7,0x2fe6a17e,0x2ed0a17e,0x2ddcad00,
0xac322c87,0xaf462a4e,0x2993adba,0xae7c2c87,0xa875afed,0x2f1aab05,0x2b5e2ffc,0x2e3facd8,0x2f302e1f,0xaee92bb7,0xafbcad00,0xadfe2d27,0xaf6e9cb6,0x2eb5ac32,0x2eb5a515,0x2dbaad72,
0xaaaa2f5a,0xaed02e99,0xacb02e99,0x2f80ad96,0x2b5eaf30,0x2fafa44e,0x2d00ae5e,0xaf1a9fd9,0xac072f02,0xab05ad27,0xad4d2e1f,0x28142e3f,0x2c5daed0,0xa9f12fff,0x2d96addc,0x2c5dafe6,
0x28752f80,0xa8d52fe6,0xa8d52fc9,0x2e3faf46,0xa44eafd4,0x2f91adba,0x2b05af6e,0xafbc26a1,0x96482ffc,0xae99a44e,0xac872ee9,0x29f12d4d,0x2515aff8,0x1cb62f02,0x2d72ae3f,0x2c32aff8,
0x2eb52b05,0x2a4e2cd8,0x16482fed,0x2c5daffc,0xad72ad27,0x2cb0aff4,0x2765aff4,0xafff2b5e,0x2bb72e7c,0xaff82aaa,0xab5e2f80,0x2bb72c32,0xa814af6e,0x2b052c87,0x2d4dae99,0x2c07b000,
0x2feda8d5,0x2f30a30e,0x29342f02,0x2814afa0,0xafd49cb6,0x1648aed0,0x1648afe6,0xafdd2d72,0x2ed029f1,0xaf462eb5,0xa9932fdd,0x2cb029f1,0xad00ad4d,0x2e1f244e,0x2d27aee9,0x2bb7affc,
0x2d4daf02,0x2fbcae1f,0x2cd82d27,0x9fd9ae3f,0xaf5a2cb0,0xac87a993,0xa6a1af46,0xaf5a2ed0,0x2fffa5db,0xacb03000,0xa7653000,0x2d7226a1,0xaf1aa814,0x2fafa934,0x2d00af30,0x2b5eafed,
0x1648afbc,0x2c87affc,0x2e992934,0xa9f1ac07,0xac322faf,0xaf8028d5,0xaaaaae1f,0xae7c2faf,0x2f1aad72,0xa30e2ed0,0xa30e2fe6,0x2e1f1cb6,0xaffc26a1,0x2fedadba,0x2cd8af6e,0x2b05afd4,
0xad27ac32,0xa30ead72,0x2faf9cb6,0xad27a515,0x1fd92f6e,0xafbc2e99,0xacd8ac87,0xad4d3000,0x2c5dafbc,0x2a4e2b05,0x16482f91,0x2eb5a44e,0xaf802d00,0x2ed0afa0,0x2cb0afa0,0x2aaaafaf,
0xafe626a1,0xaddc1648,0x2fffaa4e,0xaed026a1,0x2d002c07,0xad272ffc,0xae1fa934,0xabb72fbc,0x1fd9afa0,0x2e5ea30e,0x244e2f02,0x2f30a8d5,0xadba2f46,0x2c87afe6,0x2c87afc9,0x2a4eaf80,
0xafff2d96,0xae7c2c5d,0xafc92c5d,0x2d72a9f1,0xa17e2dfe,0xaff42fbc,0xa8752ee9,0x2ff8af30,0x2fedad00,0xad4d2f1a,0x2f91ab5e,0x2e5eafaf,0x25dbae7c,0x16482993,0x29f1af46,0x25dbac32,
0xae3f2fff,0xaff82fc9,0xaff82e7c,0x2f02ad72,0x2c0725db,0xadfe2f5a,0x9fd92d96,0x2fedafdd,0x2f6eaf91,0xa6a12c07,0x2fd4acd8,0x2dbaaf30,0xa765ab5e,0x2aaaa30e,0x2993af02,0x2515ab5e,
0xa5db2dfe,0xad962ee9,0xaf5a2fbc,0x2fddaf30,0x2f46ab5e,0xa7652bb7,0x25152bb7,0x2f80aff8,0x2d00afc9,0x28d59cb6,0x2ff8addc,0x2d00ae7c,0xacd89648,0x2dfeac5d,0x2934aeb5,0x244eaa4e,
0x2c07217e,0x9fd92875,0xadfe2ff4,0x2fedaff8,0x2fddaf46,0x29f1a515,0x29f12765,0x2eb5af80,0x2515ad96,0x2ddcac87,0x2fffaeb5,0x2c32ad96,0xaf022b05,0x2fa0aee9,0x28d5ae5e,0x230ea934,
0x2f91ad00,0x2cd8ab5e,0xac072f1a,0x2f30afaf,0x2d96afc9,0x2eb5addc,0x2c879cb6,0x2d96ae7c,0xa993a6a1,0x2fc9af5a,0x2fe6af5a,0x2aaaac87,0xaff82e5e,0x2ff4affc,0x2875adfe,0x217ea814,
0x2f6eafed,0x2fd4af91,0xa6a12d4d,0x2dbaae5e,0x2515ad00,0x2fffaff8,0x2ddca8d5,0x2c32ad00,0xae1f2993,0x2fafafe6,0x2fafafc9,0x28d5aaaa,0xaf912fdd,0x2ee9af5a,0x2814ad96,0x1fd9a5db,
0x2b5eae7c,0x2f02af46,0x230e2993,0x2b5eac32,0xab059648,0x2e5eaeb5,0x2ee9ac5d,0x2934aa4e,0xafdd2e5e,0x2d96adfe,0x2f5aaffc,0x25dba814,0xaddc2faf,0x2cb0ad27,0x2765ad27,0x1cb6a30e,
0xa765a5db,0x2993a9f1,0x2aaa9648,0x2515a5db,0xaf022cd8,0x28d5a934,0x2fa0adfe,0x230ea44e,0xaf912ff8,0x2814a875,0x2ee9aff4,0x1fd9a17e,0xaa4e2ddc,0x26a1a765,0x26a1acb0,0x16489cb6,
0x2d722d96,0x25152c5d,0x2c322c5d,0x1cb6a9f1,0x2d272d4d,0xad00a814,0x2bb72c07,0x2e1f2b05,0x2cd82d00,0xaffcaf1a,0x2b052b5e,0x2fed2faf,0x2c872cb0,0xadbaaf80,0x2a4e2aaa,0x2c872ed0,
0x2e3f2ddc,0x2ff82ed0,0x2ff82fe6,0xaf02afff,0x2ee92e99,0x2d4d2f6e,0x2ffc3000,0xa44eac87,0x2f6e2f30,0xa6a12814,0x2fd42fed,0x2dba2934,0x2fc92fa0,0xaf46ad00,0x2f802faf,0x2fe62fa0,
0xac87ad4d,0x9648ac07,0x29f12814,0xae99ab05,0xa993ab5e,0x2ed02bb7,0x2cb02bb7,0xaf46aff8,0xa30ea765,0x2f1a2fff,0x2e1f2d72,0xa30eacb0,0x244e1648,0x1fd92c5d,0x2f302eb5,0x2e5e2a4e,
0xaee9ae1f,0xaffcaf02,0xad4dae3f,0x244e2d27,0xafddaf80,0xa9f1ae7c,0xa9f1ac32,0xaeb5aaaa,0xafe6b000,0x2d7225db,0x9cb6a6a1,0xaed0b000,0xaf02af91,0x2fa02fbc,0x28d5244e,0x230eab05,
0x2b052d00,0xa44e2b5e,0xafbcaf1a,0x2f912faf,0x16482765,0xafd4ad72,0xafddafff,0x16482cb0,0xaaaaa6a1,0xac32af5a,0xae7caf5a,0xaf80ac87,0xae1facd8,0x2d001fd9,0xabb7ad4d,0xad27afbc,
0x2f6e2e5e,0x2fd42f30,0xa6a11fd9,0x2dba244e,0x2fe62ff4,0x1cb62d27,0xad72ab5e,0x2ed02ff4,0x2e1f2f46,0xafafacb0,0xafafaed0,0xa8d52993,0x29342c87,0xac07af6e,0xafbcb000,0xaffcae99,
0xa8d5acb0,0x2875aaaa,0x2e3f2f80,0xa8d5aed0,0x29341648,0x2fed2eb5,0x28142c5d,0x2f302a4e,0x2e992cd8,0x16482d4d,0xa9f19fd9,0x2c872fbc,0x2fff2faf,0xafe6ad27,0xaed0ad27,0xaddca30e,
0xafc9ae99,0xaf80af5a,0x2f462d96,0xafe6ae99,0xaf02afed,0x28d5ab05,0x2fa02ffc,0x230eacd8,0xa934ad27,0x2fbc2f02,0x2c072e3f,0x2ffc2e1f,0x2a4e1cb6,0xa6a12c32,0xa6a12515,0x96482d72,
0xaaaa29f1,0xaed025db,0xacb025db,0x2f801648,0xaf1aaf91,0x2875ae5e,0xae3fafed,0xab5e2d4d,0x2c07a875,0x2b052ff8,0x2d4da17e,0xa814aff4,0x2eb52fc9,0xaf6ead72,0x2dba2fff,0x2eb52e7c,
0x2f022f80,0x2b5e2fe6,0x2b5e2fc9,0x230eaf46,0xacd826a1,0xaf30ad96,0xaf91a9f1,0x2c072fd4,0xad96affc,0x2fdd244e,0xa5dbaee9,0xaf5aad4d,0x2e7c217e,0xad722bb7,0x2fff2d00,0x2fc9217e,
0x2c5da934,0x2f5aa44e,0x30002cd8,0xaeb5adfe,0x2d722ff8,0xacb02d00,0xa7652d00,0x2fff28d5,0xaf02a515,0x217eaf80,0xaf1aaf46,0xaf022765,0xa814af5a,0x2b052fdd,0x2d4da5db,0x2c07ad96,
0xae5eafa0,0xa934aff4,0x2b05abb7,0xaee928d5,0x2eb51cb6,0x2d962ed0,0x2d962fe6,0x2c87ad72,0x27652f6e,0xaf80ac5d,0xaf46a5db,0xa5152f6e,0xaff4ad4d,0x2ff8244e,0xa17eaee9,0xa875affc,
0xad4d2875,0xafbc217e,0xacd8aff8,0x1fd92ff4,0xaa4eafe6,0x2e99aaaa,0x2fd42993,0xaa4eafc9,0x2fff2c87,0xacb02d96,0xa7652d96,0x2d722eb5,0xab5e2c07,0x2875af30,0xae3faf91,0xaf1aacd8,
0x2d962fbc,0x25db2ffc,0xafdda934,0x2f5a2c07,0xafc9a875,0xaaaaafa0,0x2993ad27,0xafe6a875,0x28d5ad72,0x2d002ed0,0x2d002fe6,0x2ff81cb6,0x2d4d2fd4,0xae5ead96,0xafeda9f1,0xaf9126a1,
0x2e1fa765,0x2ff49cb6,0xa8752ddc,0x2e1facb0,0x1fd92f5a,0xafbc25db,0xacd8afdd,0xad4d2d96,0xaeb5aee9,0x2f5aa934,0x30002b05,0x2c5dae5e,0x2f80230e,0xaed02b5e,0xacb02b5e,0xaaaa2f02,
0xacb0afd4,0x9cb6b000,0x2ddc2f5a,0xa765afd4,0x2ff42c07,0x217e2ffc,0xaff8a934,0x28752fbc,0xadfe28d5,0xa44eaff4,0x2cd8abb7,0xa934afa0,0x1648af46,0x25db2fe6,0x25db2fc9,0x29f12f80,
0xafff9648,0xae7ca6a1,0xafc9a6a1,0x2d722a4e,0x2ff81fd9,0x230e2ee9,0x2faf2814,0x217eaf91,0xafeda30e,0x2d4dafa0,0xaf91a8d5,0xae5e2f02,0x2fdd2515,0xb0002aaa,0x2f6e2993,0x2fdda765,
0xa30e2fff,0xad272fc9,0xad272e7c,0x2fafad72,0x2814afdd,0x2ffcaa4e,0x2dfeadba,0xae5ea5db,0xaa4e2f91,0xac5dac07,0xaeb52cd8,0x96482f30,0x2c32af1a,0xa9932ff4,0x2f46abb7,0x2e7caf1a,
0x2fdd1fd9,0x2dba2814,0x2a4e2ee9,0x25dbaf91,0xaf46a8d5,0x2765afaf,0xa515afaf,0xaf802e1f,0x2e3f2c32,0xafa02ddc,0xa17e2fff,0x2e3f2515,0xacd8adba,0x2dfe26a1,0x2934afd4,0x244eaf6e,
0x2814aff8,0x2dfeafaf,0x2ffca30e,0xae5ea17e,0xac872f46,0xaf5a2515,0xaf5aa765,0xa6a12f80,0x2e7cadba,0x1cb62e99,0x2ddc2c5d,0x2fc9adba,0xafaf2b05,0x2f1aaee9,0xab5eae5e,0xad00a934,
0xaf91a30e,0xacd8a8d5,0x2c07afa0,0xaf302f02,0x2dba2c32,0xac5d2fff,0xae992ddc,0x2dba2515,0xa993aeb5,0x2fc9a9f1,0x2fe6a9f1,0x2aaaafdd,0xa17e2fed,0xa30eadfe,0xafaf9fd9,0xaff82c07,
0xaa4e2fed,0xaeb52f91,0xac5dad4d,0x96482e5e,0x2e7cae3f,0x2ddc217e,0x1cb62fa0,0x2fc9ae3f,0xaff82993,0x2bb7afe6,0x2bb7afc9,0xab5eaaaa,0x2f3025db,0xafbc2a4e,0xaee92dba,0xadfe2fdd,
0x2f1a2515,0x2bb72993,0xaff42aaa,0x2f1aa765,0xab05adba,0x2e5eafd4,0x2ee926a1,0x2934af6e,0xa5db2fed,0xadba9fd9,0xaa4eadfe,0xafdd2c07,0x2ddcaf02,0xacb02ff8,0xa7652ff8,0x9cb62e3f,
0x2c32afdd,0x2f46af6e,0xa9933000,0x2e7cafdd,0xafaf2cd8,0xab5ea934,0x2f1aadfe,0xad00a44e,0x2f30217e,0xaee92faf,0xafbc230e,0xadfe2ff8,0xa9f1addc,0x2c5d2765,0x2c5d2cb0,0x2d961cb6,
0xa993aa4e,0x2765ac87,0xa515ac87,0xaaaa2dba,0xafa02f30,0xabb7244e,0xaff42e5e,0x28d51fd9,0x28142bb7,0xaf912e1f,0x1fd92d27,0x2ee9ad00,0x2fd4aed0,0xaf5a2fff,0x3000addc,0x2fd4afe6,
0xafaf2f46,0xafa02e7c,0xafa02c32,0x2d00a993,0x244e2c5d,0xaf913000,0xab052f5a,0x2fbcaeb5,0x3000adfe,0xac872e5e,0x2e99a814,0x2f6eaffc,0x2515ae1f,0x1cb62875,0x2d72aff4,0x2c32ae1f,
0x26a12b05,0xa9f12cd8,0xad962fed,0x2fd4affc,0x2fffae1f,0x2515230e,0x2c32230e,0x2ddcaf1a,0x2875ae7c,0x2d27aaaa,0x2fa0af80,0x2875ac32,0xaee929f1,0x2f91ae99,0x9fd9ac87,0xa8149648,
0x2fedaf1a,0x2f30ae3f,0x29342875,0x2814ab5e,0x26a1addc,0x3000afc9,0x3000ae7c,0xa5db9cb6,0xaed02a4e,0x2f46afd4,0x2993ae99,0xacb02a4e,0xae3f2ffc,0x2d27ae5e,0xae1f2814,0xaf022dfe,
0x9fd9abb7,0x2c07ad27,0x2fedae1f,0xadfe2d00,0xaf6e2cb0,0x25dba993,0x2c5daf46,0xaf6e2ed0,0xaddc2fdd,0xa5159648,0xac329648,0xafff2fd4,0x28d52814,0xabb72934,0xaff42f30,0xafa02fed,
0xb0002ee9,0xae992dfe,0x2c87af30,0xaf6e2fbc,0xac322f02,0xaf802f1a,0xaaaaa17e,0xae7c2f02,0x2b5e1cb6,0xaff42fc9,0xaff42e7c,0xad272ddc,0x2ffcaeb5,0xafed3000,0xacd82f5a,0xab052c5d,
0xa17e2c32,0xad002d72,0xabb71cb6,0xa17e2515,0x2dfea9f1,0xac072c87,0xafed2e99,0x1fd91648,0x2fd4afbc,0xa9f12b05,0xad962f91,0x26a1a44e,0x2aaaae3f,0xa76528d5,0x251528d5,0x2993a875,
0x2fe6aeb5,0x2ddcadba,0xafff2f6e,0x2ed0aeb5,0x2e3fafbc,0x2e1fadfe,0xad272f30,0x2f02aee9,0x1fd9ab5e,0x2e5eae3f,0x244e2875,0x2f30af1a,0xad962993,0x2e99ae7c,0x2e99ac32,0x2f5aaf46,
0x299329f1,0xa76525db,0x251525db,0x2aaa1648,0x28d52934,0xaf02acd8,0x230e244e,0x2fa02dfe,0x28142875,0xaf91aff8,0x1fd9217e,0x2ee92ff4,0x26a12765,0xaa4eaddc,0x16481cb6,0x26a12cb0,
0x2f022f46,0x2b5e2e7c,0x2b5e2c32,0x230ea993,0x2e5e2eb5,0xab051648,0x29342a4e,0x2ee92c5d,0x2d962dfe,0xafddae5e,0x25db2814,0x2f5a2ffc,0x2cb02d27,0xaddcafaf,0x1cb6230e,0x27652d27,
0x2fd42f91,0x2f6e2fed,0x2dba2e5e,0xa6a1ad4d,0x2fff2ff8,0x25152d00,0x2c322d00,0x2ddc28d5,0x2faf2fe6,0xae1fa993,0x28d52aaa,0x2faf2fc9,0x2ee92f5a,0xaf91afdd,0x1fd925db,0x28142d96,
0x2cd82b5e,0x2f912d00,0x2f302faf,0xac07af1a,0x2eb52ddc,0x2d962fc9,0x2d962e7c,0x2c871cb6,0x2fc92f5a,0xa99326a1,0x2aaa2c87,0x2fe62f5a,0x2ff42ffc,0xaff8ae5e,0x217e2814,0x28752dfe,
0x9fd9a875,0x2c07a17e,0x2fed2ff8,0xadfeaff4,0x29f12515,0x2fdd2f46,0x2eb52f80,0x29f1a765,0x2ddc2c87,0x25152d96,0x2c322d96,0x2fff2eb5,0x2fa02ee9,0xaf02ab05,0x230e2934,0x28d52e5e,
0xad96aee9,0xa5dbadfe,0x2fdd2f30,0xaf5aafbc,0xa765abb7,0x2f462b5e,0x2f802ff8,0x2515abb7,0x28d51cb6,0x2d002fc9,0x2d002e7c,0x2ff82ddc,0x2dfe2c5d,0xacd81648,0x244e2a4e,0x29342eb5,
0xaff8afc9,0xae3fafff,0x2f022d72,0xaff8ae7c,0xadfeaf5a,0x2c07a5db,0x2fed2fdd,0x9fd9ad96,0xa6a1ac07,0x2f6e2f91,0x2dba2f30,0x2fd42cd8,0x2aaa230e,0xa7652b5e,0x25152b5e,0x29932f02,
0xae7cac5d,0xafffad96,0x2d7229f1,0xafc9ac5d,0xaff4afbc,0xa17eadfe,0x2ff82f30,0xa875aee9,0xad4daf1a,0x2fed2d00,0x2e5e2faf,0x2f912b5e,0x1648a993,0x25db2e7c,0x25db2c32,0x29f12f46,
0xaddc9648,0xafe6a6a1,0xaed0a6a1,0x2fff2a4e,0xad27affc,0x2d00ac07,0xabb7afbc,0xae1f2934,0x2e5e230e,0x1fd92fa0,0x2f3028d5,0x244eaf02,0x2c872fe6,0xadbaaf46,0x2a4e2f80,0x2c872fc9,
0xa30e2d72,0xad272c32,0xad272515,0x2faf1cb6,0xafbcae99,0x1fd9af6e,0xad4db000,0xacd82c87,0x2a4eab05,0x2c5d2fbc,0x2eb5244e,0x1648af91,0x2ed02fa0,0xaf80ad00,0x2aaa2faf,0x2cb02fa0,
0x2c872ffc,0x16482fbc,0xa9f12c07,0x2e99a934,0xaf80a8d5,0xac32afaf,0xae7cafaf,0xaaaa2e1f,0xa30eaed0,0x2f1a2d72,0x2e1f9cb6,0xa30eafe6,0x2fed2dba,0xaffca6a1,0x2b052fd4,0x2cd82f6e,
0x2fbc2e1f,0x2d4d2f02,0x9fd92e3f,0x2cd8ad27,0xac872993,0xaf5aacb0,0xaf5aaed0,0xa6a12f46,0xacb0b000,0x2fff25db,0x2d72a6a1,0xa765b000,0x2faf2934,0xaf1a2814,0x2b5e2fed,0x2d002f30,
0x2f30230e,0x2fed28d5,0x28142fa0,0x2934af02,0x16482ed0,0xafd41cb6,0xafddad72,0x16482fe6,0xaf46aeb5,0x2ed0a9f1,0x2cb0a9f1,0xa993afdd,0x2e1fa44e,0xad002d4d,0x2bb72ffc,0x2d272ee9,
0x2a4eacd8,0x2eb5ab05,0x2c5d2ffc,0x1648afed,0x2cb02ff4,0xad722d27,0xafffab5e,0x27652ff4,0xaff8aaaa,0x2bb7ae7c,0x2bb7ac32,0xab5eaf80,0x2b05ac87,0xa8142f6e,0x2c073000,0x2d4d2e99,
0xa8d5afe6,0x2875af80,0x2e3f2f46,0xa8d5afc9,0x2f912dba,0xa44e2fd4,0xafbca6a1,0x2b052f6e,0xae99244e,0x9648affc,0x29f1ad4d,0xac87aee9,0x1cb6af02,0x25152ff8,0x2c322ff8,0x2d722e3f,
0xaed0ae99,0xaaaaaf5a,0x2f802d96,0xacb0ae99,0x2faf244e,0x2b5e2f30,0xaf1a1fd9,0x2d002e5e,0xab052d27,0xac07af02,0x2814ae3f,0xad4dae1f,0xa9f1afff,0x2c5d2ed0,0x2c5d2fe6,0x2d962ddc,
0xaf46aa4e,0xac32ac87,0xae7cac87,0x29932dba,0x2f1a2b05,0xa8752fed,0x2e3f2cd8,0x2b5eaffc,0xaee9abb7,0x2f30ae1f,0xadfead27,0xafbc2d00,0x2eb52c32,0xaf6e1cb6,0x2dba2d72,0x2eb52515,
0xafaf2993,0xafa02515,0xafa0a765,0x2d002aaa,0x2feda6a1,0x29342d96,0x2f3029f1,0x2814afd4,0xb0001fd9,0x2c87afed,0xae99ac07,0xaf6e2dfe,0x2fe6217e,0xafff2bb7,0x2ddc2d00,0x2ed0217e,
0xac5d2f30,0xaf5a2e5e,0xb000244e,0x2eb51fd9,0x2ddcae1f,0x2e7c230e,0x2fc9230e,0x1cb6af1a,0xaf022cb0,0x217eaf46,0xaf1aa993,0xaf022ed0,0x2fbca9f1,0xaf302e99,0x2dfe2c87,0x2ee91648,
0x244e2fa0,0xab052ff4,0xaf912bb7,0x2fbca8d5,0x26a1afff,0x3000ac32,0x3000a515,0xa5dbaddc,0xac322f6e,0xaaaaac5d,0xaf80a5db,0xae7c2f6e,0x2e3fadfe,0xad272fed,0x2e1f2c07,0x2f029fd9,
0x2dfe2bb7,0x28142d27,0xae5e2e1f,0x2ffcad00,0xaa4eae7c,0x2e99af80,0x2fd4aaaa,0xaa4eac32,0x9cb62fdd,0xae7c9648,0xafc99648,0xaddc2fd4,0x2b5eafbc,0xa8752f91,0x2e3f2b05,0x2f1aa44e,
0x3000a814,0x2e999fd9,0xac872f91,0x2f6eaee9,0xaed0a875,0x2993afa0,0x2f46ad27,0xacb0a875,0x2b5e2ddc,0xaff42c32,0xaff42515,0xad272fff,0x1fd9afd4,0x244e2d96,0x2e5e29f1,0x2f30a6a1,
0x2e1faed0,0x2ff4addc,0xa8752fff,0x2e1fafe6,0xaffc29f1,0xa814ac87,0x2e5eae99,0xadfe9648,0x2eb52814,0xaf5a2f30,0xb0002934,0xac5d2fed,0xa993ae3f,0x2c3228d5,0x2e7c28d5,0x2f46a875,
0x2515afd4,0x2d72b000,0x1cb62f5a,0x2c32afd4,0xae3f2ee9,0xae1f1fd9,0x2d27af91,0xaf022814,0x2ffca8d5,0xacd82ff4,0xafed2bb7,0xab052fa0,0xad96aaaa,0x2e99a515,0x2e992765,0x2f5aa993,
0x1cb6adba,0x2cb0aeb5,0x2765aeb5,0xaddc2f6e,0xaff82d4d,0xa30ea814,0xafaf2c07,0xa17e2b05,0xa44e2e3f,0xadfe2b5e,0xa9342f1a,0x2cd8a875,0x2fddacb0,0xb0002f80,0x2f6eaaaa,0x2fddaed0,
0xad009cb6,0xa17ea765,0xa17eacb0,0xabb72ddc,0xaee92fdd,0xad4d2a4e,0xaffc2dba,0x244e25db,0x29f12934,0xafd42ee9,0xa6a12e5e,0x2d96ab05,0x2fc9af1a,0xaf462ff4,0x2f80abb7,0x2fe6af1a,
0xafdd2d4d,0xadba2c07,0xaa4ea814,0xa5db2b05,0xaaaa2f1a,0xafc92f02,0xafe62f02,0x2993a17e,0x2e3fa765,0xafa02fff,0xa17e2d72,0x2e3facb0,0x2e5eb000,0xad4d2eb5,0x2f91ac5d,0x2fedaf5a,
0xaee92ff8,0xaffc2faf,0xad4d230e,0x244e217e,0x25db2aaa,0xaf6e2fe6,0xaf6e2fc9,0x2c5da993,0x2fe6adba,0xad722e99,0x1cb62c5d,0x2ed0adba,0x2bb7af30,0xa8d52c07,0x2fa0acd8,0x2ff4af91,
0xa9342e3f,0xae5e2f1a,0xaee92b5e,0x2b05a875,0x2dbaa765,0xac5d2d72,0xae992fff,0x2dbaacb0,0x2f80afd4,0xa7652a4e,0x25152a4e,0x2f46ae99,0x217eacd8,0x230e1fd9,0x2fafad4d,0x2ff8afbc,
0x29f1244e,0xa6a12934,0xafd42dfe,0x2d96acd8,0x2fe6ae3f,0x1cb6217e,0xad722fa0,0x2ed0ae3f,0x2d27af80,0x2875a515,0x28752765,0x2fa0af46,0xa934a5db,0x2c07aa4e,0x2fbcadba,0x2ffcafdd,
0x2f1aacb0,0x2bb7aaaa,0xaff42f80,0x2f1aaed0,0x2f30b000,0x2cd8ac5d,0xac072eb5,0x2f91af5a,0x25dbacd8,0x2dbaad4d,0x2a4e1fd9,0x2fddafbc,0xad722875,0x2e7cae1f,0x2fc9ae1f,0x2fffaff4,
0x2fc9afdd,0x2f80af6e,0xaf463000,0x2fe6afdd,0x2bb7ae5e,0x2fa0af91,0xa8d52d4d,0x2ff4afed,0xa934a17e,0x2fbcafaf,0x2c07a30e,0x2ffcaff8,0xaf5a2d72,0x2fd4afc9,0x2fd4ae7c,0x3000afff,
0x3c003c00,0x3bff3c00,0x3c003c00,0x3bfa3bfd,0x3c003c00,0x3bef3bf5,0x3c003c00,0x3bde3be7,0x3c003c00,0x3bc83bd4,0x3c003c00,0x3bac3bbb,0x3c003c00,0x3b8b3b9d,0x3bff3c00,0x3b653b79,
0x3c003c00,0x3bff3c00,0x3c003c00,0x3bf83bfd,0x3bff3c00,0x3bea3bf2,0x3bff3bff,0x3bd63be1,0x3bfe3bff,0x3bba3bc9,0x3bfd3bfe,0x3b983baa,0x3bfc3bfd,0x3b6f3b84,0x3bfb3bfc,0x3b3f3b58,
0x3c003c00,0x3bff3c00,0x3bff3c00,0x3bf63bfc,0x3bfe3bff,0x3be53bef,0x3bfd3bfe,0x3bcc3bda,0x3bfb3bfc,0x3bab3bbc,0x3bf93bfa,0x3b813b97,0x3bf63bf7,0x3b4f3b69,0x3bf23bf4,0x3b163b33,
0x3c003c00,0x3bff3c00,0x3bff3c00,0x3bf53bfb,0x3bfd3bfe,0x3be03bec,0x3bfa3bfc,0x3bc23bd2,0x3bf63bf8,0x3b9a3baf,0x3bf23bf4,0x3b683b82,0x3bec3bef,0x3b2c3b4b,0x3be53be9,0x3ae83b0b,
0x3c003c00,0x3bfe3c00,0x3bfe3bff,0x3bf23bfa,0x3bfb3bfd,0x3bda3be8,0x3bf63bf9,0x3bb73bca,0x3bf03bf4,0x3b873ba0,0x3be83bed,0x3b4c3b6b,0x3bdf3be4,0x3b073b2b,0x3bd43bda,0x3ab63ae0,
0x3c003c00,0x3bfe3c00,0x3bfd3bff,0x3bf03bf9,0x3bf93bfb,0x3bd43be4,0x3bf23bf6,0x3bab3bc1,0x3be83bed,0x3b733b91,0x3bdd3be3,0x3b2f3b53,0x3bcf3bd6,0x3ade3b08,0x3bbf3bc7,0x3a813ab1,
0x3c003c00,0x3bfe3c00,0x3bfc3bfe,0x3bee3bf8,0x3bf63bf9,0x3bce3be0,0x3bec3bf1,0x3b9e3bb7,0x3bdf3be6,0x3b5e3b80,0x3bcf3bd7,0x3b103b39,0x3bbc3bc6,0x3ab33ae3,0x3ba53bb1,0x3a493a7f,
0x3bff3c00,0x3bfe3c00,0x3bfb3bfe,0x3beb3bf7,0x3bf23bf7,0x3bc63bdb,0x3be53bed,0x3b903bad,0x3bd43bdd,0x3b473b6e,0x3bbf3bca,0x3aee3b1d,0x3ba53bb2,0x3a853abc,0x3b873b97,0x3a0d3a4b,
0x3bfd3c00,0x3bfa3c00,0x3be83bf6,0x3bcc3be9,0x3bbf3bd6,0x3b713ba4,0x3b813ba2,0x3aeb3b33,0x3b2f3b5a,0x3a3d3a99,0x3acb3aff,0x396b39d8,0x3a543a92,0x387a38f6,0x39cd3a13,0x36dd37ee,
0x3bfd3c00,0x3bfa3c00,0x3be53bf4,0x3bc83be7,0x3bb73bd1,0x3b653b9d,0x3b713b97,0x3ad53b22,0x3b163b46,0x3a193a7c,0x3aa53ae0,0x393739ad,0x3a213a65,0x383538ba,0x398b39d8,0x36313753,
0x3bfd3c00,0x3bf93c00,0x3be23bf3,0x3bc33be5,0x3bae3bcb,0x3b593b95,0x3b603b8a,0x3abd3b11,0x3afb3b30,0x39f43a5e,0x3a7e3abf,0x39023980,0x39eb3a37,0x37dd387c,0x3946399b,0x358136b5,
0x3bfc3c00,0x3bf93c00,0x3bdf3bf1,0x3bbf3be3,0x3ba53bc6,0x3b4c3b8c,0x3b4f3b7d,0x3aa53aff,0x3ade3b1a,0x39cd3a3f,0x3a543a9c,0x38cc3951,0x39b33a07,0x374e383d,0x38fd395b,0x34cf3614,
0x3bfc3c00,0x3bf83c00,0x3bdc3bf0,0x3bba3be1,0x3b9c3bc0,0x3b3f3b84,0x3b3d3b70,0x3a8c3aed,0x3ac13b02,0x39a63a1f,0x3a293a78,0x38943922,0x397939d4,0x36bb37f9,0x38b23918,0x341a3570,
0x3bfc3c00,0x3bf83c00,0x3bd83bee,0x3bb53bdf,0x3b923bb9,0x3b323b7b,0x3b2a3b62,0x3a733ad9,0x3aa23ae9,0x397d39fe,0x39fc3a52,0x385a38f1,0x393c399f,0x36253775,0x386538d3,0x32c634c9,
0x3bfb3c00,0x3bf73c00,0x3bd43bed,0x3bb03bdc,0x3b873bb2,0x3b243b72,0x3b163b53,0x3a583ac6,0x3a813ad0,0x395439dc,0x39cd3a2b,0x382038bf,0x38fd3969,0x358d36ee,0x3815388c,0x31533420,
0x3bfb3c00,0x3bf63c00,0x3bd03beb,0x3bab3bda,0x3b7c3bab,0x3b163b69,0x3b013b43,0x3a3d3ab1,0x3a603ab5,0x392939ba,0x399d3a02,0x37c8388c,0x38bc3930,0x34f33665,0x37853842,0x2fbd32ea,
0x3bf63c00,0x3bf03c00,0x3ba53bd7,0x3b733bc1,0x3b073b5f,0x3a813b08,0x3a213a9c,0x392939e1,0x38fd3996,0x36ff385d,0x374e3858,0x327c3529,0x345735da,0xa9b12d1a,0x2cce3191,0xb49fb160,
0x3bf53c00,0x3bef3c00,0x3b9f3bd5,0x3b6c3bbe,0x3af73b55,0x3a6f3afc,0x3a043a87,0x390739c7,0x38d13972,0x36993832,0x36d23822,0x316c34b1,0x3371354c,0xad65297f,0x27763036,0xb552b2b9,
0x3bf53c00,0x3bef3c00,0x3b9a3bd2,0x3b653bbb,0x3ae83b4b,0x3a5c3af0,0x39e73a71,0x38e539ad,0x38a3394d,0x36313807,0x365437d8,0x305b3438,0x323234bd,0xafef1e48,0xa4522db0,0xb602b408,
0x3bf43c00,0x3bee3c00,0x3b943bd0,0x3b5e3bb7,0x3ad83b41,0x3a493ae3,0x39c93a5a,0x38c13992,0x38743927,0x35c837b7,0x35d4376a,0x2e91337d,0x30f0342c,0xb13ba7da,0xac0629e3,0xb6afb4b1,
0x3bf33c00,0x3bed3c00,0x3b8e3bcd,0x3b573bb4,0x3ac73b36,0x3a353ad6,0x39aa3a43,0x389e3976,0x38453900,0x355e375e,0x355236f9,0x2c6a3288,0x2f593334,0xb27cac51,0xaef51a48,0xb759b558,
0x3bf23c00,0x3bec3c00,0x3b873bca,0x3b4f3bb1,0x3ab63b2b,0x3a213ac9,0x398b3a2b,0x387a395b,0x381538d8,0x34f33705,0x34cf3687,0x28843191,0x2cce320d,0xb3baaeaa,0xb0f0a91b,0xb7feb5fd,
0x3bf23c00,0x3beb3c00,0x3b813bc7,0x3b473bad,0x3aa53b20,0x3a0d3abc,0x396b3a13,0x3855393e,0x37c838b0,0x348736aa,0x344b3614,0x16483099,0x288430e4,0xb47bb080,0xb263ad4c,0xb850b69e,
0x3bf13c00,0x3bea3c00,0x3b7a3bc4,0x3b3f3baa,0x3a933b14,0x39f83aae,0x394a39fa,0x38303922,0x37643887,0x341a364e,0x3389359f,0xa81f2f40,0x9cb62f72,0xb517b1aa,0xb3d3b004,0xb89eb73d,
0x3be93c00,0x3be13c00,0x3b373ba6,0x3af13b86,0x39e33aa0,0x392e3a27,0x380a3905,0x3599380d,0x335935f1,0x217f31db,0xac382d4c,0xb546b12e,0xb5b1b2d2,0xb90cb7cd,0xb8eab7d8,0xbadbba0b,
0x3be83c00,0x3be03c00,0x3b2f3ba2,0x3ae83b82,0x39cd3a92,0x39163a17,0x37c838e7,0x354637d8,0x327c3593,0xa4523115,0xae5f2aac,0xb5c8b226,0xb648b3f7,0xb94ab828,0xb933b838,0xbb0aba43,
0x3be73c00,0x3bdf3c00,0x3b273b9e,0x3ade3b7d,0x39b83a83,0x38fd3a07,0x377a38c9,0x34f33796,0x319e3534,0xa9b1304e,0xb042257f,0xb648b31b,0xb6ddb48d,0xb986b867,0xb979b881,0xbb35ba78,
0x3be63c00,0x3bde3c00,0x3b1e3b9b,0x3ad53b79,0x39a13a74,0x38e539f6,0x372c38ab,0x349f3753,0x30be34d5,0xac9c2f0e,0xb153a0b6,0xb6c6b408,0xb76fb51d,0xb9c0b8a6,0xb9bcb8c9,0xbb5cbaaa,
0x3be53c00,0x3bdd3c00,0x3b163b97,0x3acb3b74,0x398b3a65,0x38cc39e5,0x36dd388c,0x344b3710,0x2fbd3475,0xae5f2d7e,0xb263a91b,0xb742b481,0xb7feb5ab,0xb9f8b8e2,0xb9fcb90e,0xbb7fbad9,
0x3be43c00,0x3bdc3c00,0x3b0d3b93,0x3ac13b70,0x39743a56,0x38b239d4,0x368d386d,0x33eb36cc,0x2dfb3414,0xb0102bd9,0xb371ac83,0xb7bdb4f9,0xb845b637,0xba2db91d,0xba39b951,0xbb9ebb05,
0x3be33c00,0x3bda3c00,0x3b043b8f,0x3ab63b6b,0x395d3a47,0x389939c3,0x363c384d,0x33403687,0x2c383365,0xb0f028b6,0xb43eae78,0xb81ab570,0xb889b6c1,0xba60b956,0xba73b992,0xbbb8bb2e,
0x3be23c00,0x3bd93c00,0x3afb3b8a,0x3aac3b67,0x39463a37,0x387f39b1,0x35eb382d,0x32943642,0x28e832a1,0xb1cf2248,0xb4c3b036,0xb855b5e5,0xb8ccb748,0xba90b98d,0xbaa9b9d0,0xbbcfbb53,
0x3c003c00,0x3bfe3c00,0x3c003c00,0x3bf73bfc,0x3c003c00,0x3beb3bf2,0x3c003c00,0x3bd93be3,0x3c003c00,0x3bc13bce,0x3c003c00,0x3ba53bb4,0x3c003c00,0x3b823b94,0x3bff3bff,0x3b5b3b6f,
0x3c003c00,0x3bfe3c00,0x3c003c00,0x3bf53bfb,0x3bff3c00,0x3be63bee,0x3bff3bff,0x3bcf3bdb,0x3bfe3bfe,0x3bb23bc1,0x3bfd3bfe,0x3b8e3ba1,0x3bfc3bfd,0x3b643b7a,0x3bfb3bfb,0x3b333b4c,
0x3c003c00,0x3bfe3c00,0x3bff3c00,0x3bf33bf9,0x3bfe3bff,0x3be03beb,0x3bfd3bfd,0x3bc53bd3,0x3bfb3bfc,0x3ba13bb4,0x3bf83bf9,0x3b753b8c,0x3bf53bf7,0x3b413b5c,0x3bf23bf3,0x3b063b25,
0x3c003c00,0x3bfd3c00,0x3bff3bff,0x3bf03bf8,0x3bfc3bfe,0x3bda3be6,0x3bf93bfb,0x3bb93bca,0x3bf53bf7,0x3b8e3ba5,0x3bf03bf3,0x3b5a3b75,0x3beb3bee,0x3b1c3b3c,0x3be43be7,0x3ad53afa,
0x3c003c00,0x3bfd3c00,0x3bfe3bff,0x3bee3bf7,0x3bfa3bfc,0x3bd33be2,0x3bf53bf8,0x3bac3bc1,0x3bee3bf2,0x3b7a3b94,0x3be63beb,0x3b3c3b5c,0x3bdd3be2,0x3af43b19,0x3bd13bd7,0x3aa13acb,
0x3bff3c00,0x3bfc3c00,0x3bfc3bfe,0x3beb3bf5,0x3bf73bfa,0x3bcb3bdd,0x3bf03bf4,0x3b9e3bb6,0x3be63beb,0x3b643b82,0x3bda3be0,0x3b1c3b41,0x3bcb3bd3,0x3ac83af4,0x3bba3bc3,0x3a683a9a,
0x3bff3c00,0x3bfb3bff,0x3bfb3bfd,0x3be73bf3,0x3bf43bf8,0x3bc33bd7,0x3be93bef,0x3b8f3bab,0x3bdb3be3,0x3b4c3b6f,0x3bca3bd3,0x3afa3b25,0x3bb63bc1,0x3a9a3acb,0x3b9f3bab,0x3a2c3a65,
0x3bff3c00,0x3bfb3bff,0x3bf93bfd,0x3be43bf2,0x3bf03bf5,0x3bba3bd1,0x3be23be9,0x3b7f3b9f,0x3bcf3bd9,0x3b333b5b,0x3bb93bc5,0x3ad53b06,0x3b9e3bac,0x3a683aa1,0x3b7f3b8f,0x39ec3a2c,
0x3bfa3bff,0x3bf33bff,0x3be03bf0,0x3bba3bdc,0x3bb13bcb,0x3b533b8c,0x3b6e3b92,0x3ac33b10,0x3b183b45,0x3a0c3a6c,0x3aaf3ae5,0x393139a3,0x3a343a73,0x383938b9,0x39a939f1,0x36513767,
0x3bf93bff,0x3bf23bfe,0x3bdc3bee,0x3bb43bd9,0x3ba73bc5,0x3b453b82,0x3b5c3b85,0x3aa93afd,0x3afb3b2e,0x39e43a4c,0x3a863ac3,0x38fa3973,0x39fd3a44,0x37e03878,0x396339b2,0x359c36c3,
0x3bf93bff,0x3bf13bfe,0x3bd83beb,0x3bae3bd6,0x3b9d3bbe,0x3b373b78,0x3b493b76,0x3a8f3ae9,0x3add3b16,0x39bb3a2a,0x3a5b3a9f,0x38c03942,0x39c43a12,0x374b3836,0x39193971,0x34e4361d,
0x3bf83bff,0x3bf03bfe,0x3bd33be9,0x3ba73bd3,0x3b923bb6,0x3b273b6e,0x3b353b67,0x3a733ad4,0x3abe3afd,0x39913a08,0x3a2e3a79,0x38853910,0x398839de,0x36b237e6,0x38cd392d,0x34293573,
0x3bf73bff,0x3bee3bfe,0x3bcf3be7,0x3ba13bcf,0x3b873baf,0x3b183b64,0x3b203b57,0x3a573abe,0x3a9d3ae2,0x396539e4,0x39ff3a51,0x384938dc,0x394939a7,0x3617375c,0x387e38e6,0x32d834c6,
0x3bf63bff,0x3bed3bfe,0x3bca3be4,0x3b9a3bcc,0x3b7b3ba6,0x3b073b58,0x3b0a3b47,0x3a3a3aa8,0x3a7b3ac6,0x393939bf,0x39cf3a28,0x380b38a7,0x3908396e,0x357936cf,0x382c389d,0x315a3417,
0x3bf53bff,0x3bec3bfe,0x3bc53be2,0x3b933bc8,0x3b6e3b9e,0x3af73b4d,0x3af43b35,0x3a1c3a91,0x3a573aa9,0x390b399a,0x399c39fd,0x37993871,0x38c53934,0x34d8363f,0x37af3851,0x2fb032cc,
0x3bf43bff,0x3beb3bfe,0x3bbf3bdf,0x3b8c3bc5,0x3b613b95,0x3ae53b41,0x3adc3b23,0x39fd3a79,0x3a323a8b,0x38dc3973,0x396739d1,0x37183839,0x388038f7,0x343535ae,0x37023803,0x2ca93166,
0x3be93bfd,0x3bdd3bfc,0x3b853bc1,0x3b413b9e,0x3ad43b35,0x3a343ac8,0x39de3a61,0x38c53988,0x38ac394b,0x361737e0,0x36963800,0x30863435,0x3322351a,0xaecf2484,0x267b2ffb,0xb590b352,
0x3be83bfd,0x3bdb3bfc,0x3b7d3bbd,0x3b383b99,0x3ac13b29,0x3a1e3ab9,0x39bd3a48,0x389f396a,0x387b3923,0x35a83783,0x3611378e,0x2ecf336b,0x31d53484,0xb0b8a54d,0xa5b22d26,0xb645b45a,
0x3be63bfd,0x3bd93bfc,0x3b753bb9,0x3b2e3b94,0x3aaf3b1c,0x3a083aa9,0x399c3a2e,0x3878394b,0x384938fa,0x35373724,0x358a3718,0x2c903269,0x308633d9,0xb207ab8e,0xac77289d,0xb6f6b508,
0x3be53bfd,0x3bd73bfb,0x3b6d3bb5,0x3b253b8f,0x3a9b3b0f,0x39f13a9a,0x397a3a14,0x3851392d,0x381638cf,0x34c636c3,0x350236a1,0x289d3166,0x2e6b32a7,0xb352ae39,0xaf7ea052,0xb7a4b5b3,
0x3be33bfd,0x3bd53bfb,0x3b653bb0,0x3b1b3b8a,0x3a883b01,0x39d93a8a,0x395739f9,0x3829390d,0x37c538a4,0x34543662,0x34783628,0x12483061,0x2b8e3172,0xb44eb055,0xb141aac5,0xb826b65c,
0x3be23bfd,0x3bd33bfb,0x3b5c3bac,0x3b103b85,0x3a733af4,0x39c13a79,0x393439de,0x380038ed,0x375c3878,0x33c035ff,0x33d935ae,0xa86b2eb6,0x2484303c,0xb4f0b18b,0xb2bfae39,0xb878b702,
0x3be03bfc,0x3bd13bfb,0x3b533ba7,0x3b063b7f,0x3a5f3ae5,0x39a93a68,0x391039c1,0x37af38cd,0x36f1384c,0x32d8359c,0x32bf3531,0xac772ca9,0xa6162e07,0xb590b2bf,0xb41db086,0xb8c8b7a4,
0x3bde3bfc,0x3bcf3bfb,0x3b4b3ba3,0x3afb3b7a,0x3a4a3ad7,0x39913a57,0x38eb39a5,0x375c38ac,0x3684381e,0x31ee3537,0x31a434b4,0xaeb62934,0xac2b2b2a,0xb62eb3f1,0xb4d8b1ee,0xb914b821,
0x3bcd3bfa,0x3bbb3bf8,0x3af03b74,0x3a933b43,0x39783a46,0x38a239b0,0x3707388b,0x344736e0,0x310334d2,0xacdb2e39,0xb07a2052,0xb690b3e5,0xb6c9b490,0xb991b87e,0xb95eb86e,0xbb30ba79,
0x3bcb3bfa,0x3bb93bf8,0x3ae53b6e,0x3a863b3c,0x395e3a34,0x3885399c,0x36b23869,0x33d93696,0x3016346c,0xaeb62c90,0xb197a616,0xb713b472,0xb761b526,0xb9ccb8be,0xb9a5b8b9,0xbb58baad,
0x3bc93bfa,0x3bb63bf8,0x3ada3b68,0x3a793b35,0x39443a22,0x38693988,0x365c3846,0x3322364b,0x2e523405,0xb04829ca,0xb2b3ab2a,0xb793b4f0,0xb7f6b5b9,0xba05b8fc,0xb9e8b901,0xbb7dbadd,
0x3bc73bfa,0x3bb43bf7,0x3acf3b62,0x3a6c3b2e,0x392a3a10,0x384c3973,0x36053824,0x326935ff,0x2c77333a,0xb13424e9,0xb3cdada3,0xb809b56d,0xb844b64b,0xba3cb939,0xba28b947,0xbb9dbb0a,
0x3bc53bf9,0x3bb13bf7,0x3ac33b5c,0x3a5f3b27,0x391039fd,0x382e395e,0x35ae3800,0x31b035b3,0x29343269,0xb21f9f12,0xb472afb0,0xb846b5e8,0xb88bb6da,0xba70b973,0xba65b98a,0xbbb9bb34,
0x3bc23bf9,0x3baf3bf7,0x3ab73b56,0x3a513b20,0x38f539ea,0x38113949,0x355537ba,0x30f63567,0x21e43197,0xb309a839,0xb4fcb0de,0xb883b662,0xb8cfb767,0xbaa1b9ab,0xba9db9ca,0xbbd0bb5a,
0x3bc03bf9,0x3bac3bf7,0x3aab3b50,0x3a443b19,0x38d939d7,0x37e63934,0x34fc3772,0x303c351a,0xa48430c5,0xb3f1ab8e,0xb584b1e2,0xb8beb6da,0xb912b7f1,0xbacfb9e2,0xbad2ba08,0xbbe3bb7c,
0x3bbe3bf9,0x3ba93bf6,0x3a9f3b49,0x3a363b12,0x38be39c4,0x37a9391e,0x34a23729,0x2f0134cc,0xa9fd2fe2,0xb46cad71,0xb60bb2e4,0xb8f7b750,0xb953b83c,0xbafaba16,0xbb03ba42,0xbbf1bb9a,
0x96488000,0xa6ad8000,0x9cb69a48,0xad00aaac,0x9fdb9e48,0xb029aeaa,0xa17fa0b6,0xb1cfb0fd,0xa311a248,0xb371b2a1,0xa452a3db,0xb487b420,0xa51ba4b6,0xb552b4ed,0xa5e4a57f,0xb61ab5b6,
0x9cb68000,0xa7768000,0xa311a0b6,0xad97ab75,0xa5e4a4b6,0xb0a6af72,0xa81fa711,0xb27cb191,0xa94da8b6,0xb426b365,0xaa7aa9e3,0xb50bb499,0xaba7ab11,0xb5ebb57c,0xac6aac1f,0xb6c6b659,
0x9fdb8000,0xa81f8000,0xa5e4a3db,0xae2dac1f,0xa8e8a7da,0xb122b01d,0xaadea9e3,0xb328b226,0xac6aabd9,0xb493b414,0xad65ace7,0xb58db511,0xae5fade2,0xb682b608,0xaf59aedc,0xb76fb6f9,
0xa17f8000,0xa8848000,0xa81fa57f,0xaec3ac83,0xaadea97f,0xb19eb080,0xacceac1f,0xb3d3b2b9,0xae2dad7e,0xb4ffb475,0xaf8baedc,0xb60eb587,0xb074b01d,0xb715b693,0xb122b0cb,0xb80ab796,
0xa3118000,0xa8e88000,0xa94da711,0xaf59ace7,0xac6aab11,0xb219b0e4,0xae2dad4c,0xb43eb34c,0xafefaf0e,0xb56ab4d5,0xb0d7b067,0xb68db5fd,0xb1b6b147,0xb7a6b71b,0xb294b226,0xb85ab817,
0xa4528000,0xa94d8000,0xaa7aa852,0xafefad4c,0xad65ac51,0xb294b147,0xaf8bae78,0xb493b3df,0xb0d7b04e,0xb5d4b534,0xb1e8b160,0xb70ab670,0xb2f7b26f,0xb81ab7a1,0xb402b37d,0xb8a8b862,
0xa51b8000,0xa9b18000,0xaba7a91b,0xb042adb0,0xae5fad1a,0xb30fb1aa,0xb074afa4,0xb4e7b438,0xb1b6b115,0xb63cb593,0xb2f7b257,0xb785b6e3,0xb41ab396,0xb85fb812,0xb4b7b469,0xb8f3b8ab,
0xa5e48000,0xaa168000,0xac6aa9e3,0xb08dae14,0xaf59ade2,0xb389b20d,0xb122b067,0xb53ab481,0xb294b1db,0xb6a4b5f1,0xb402b34c,0xb7feb753,0xb4b7b45d,0xb8a3b852,0xb56ab511,0xb93cb8f1,
0xaa7a8000,0xacce8000,0xb0d7ae78,0xb328b0cb,0xb402b26f,0xb5dfb4bd,0xb58db4c9,0xb805b6f9,0xb70ab64e,0xb902b887,0xb83ab7c2,0xb9e3b976,0xb8e5b891,0xbaa2ba47,0xb982b935,0xbb3abaf3,
0xaade8000,0xad008000,0xb122aedc,0xb371b0fd,0xb43eb2d2,0xb61ab4ed,0xb5dfb511,0xb82ab73d,0xb76fb6aa,0xb92eb8b0,0xb874b817,0xba11b9a4,0xb924b8ce,0xbaceba74,0xb9c5b976,0xbb60bb1d,
0xab438000,0xad338000,0xb16caf40,0xb3bab12e,0xb47bb334,0xb654b51d,0xb631b558,0xb850b780,0xb7d2b705,0xb958b8d8,0xb8adb84d,0xba3db9d0,0xb962b909,0xbaf7baa0,0xba04b9b5,0xbb83bb43,
0xaba78000,0xad658000,0xb1b6afa4,0xb402b160,0xb4b7b396,0xb68db54c,0xb682b59f,0xb874b7c2,0xb81ab75e,0xb982b900,0xb8e5b881,0xba67b9fa,0xb99db943,0xbb1ebac9,0xba41b9f2,0xbba1bb67,
0xac068000,0xad978000,0xb201b004,0xb426b191,0xb4f3b3f7,0xb6c6b57c,0xb6d2b5e5,0xb899b802,0xb84ab7b7,0xb9aab927,0xb91bb8b5,0xba90ba23,0xb9d6b97b,0xbb42baf0,0xba7aba2b,0xbbbcbb86,
0xac388000,0xadc98000,0xb24bb036,0xb44bb1c3,0xb52fb42c,0xb6ffb5ab,0xb721b62b,0xb8bcb822,0xb87ab807,0xb9d2b94d,0xb94fb8e7,0xbab6ba4b,0xba0db9b1,0xbb63bb14,0xbab0ba62,0xbbd2bba2,
0xac6a8000,0xadfb8000,0xb294b067,0xb46fb1f4,0xb56ab45d,0xb737b5da,0xb76fb670,0xb8e0b842,0xb8a8b832,0xb9f8b972,0xb982b918,0xbadbba71,0xba41b9e5,0xbb81bb36,0xbae1ba95,0xbbe3bbbb,
0xac9c8000,0xae2d8000,0xb2deb099,0xb493b226,0xb5a5b48d,0xb76fb608,0xb7bdb6b5,0xb902b862,0xb8d6b85d,0xba1db996,0xb9b3b948,0xbafeba95,0xba73ba17,0xbb9cbb55,0xbb10bac6,0xbbf1bbd0,
0xae5f8000,0xafef8000,0xb4b7b257,0xb5d4b3df,0xb7a6b637,0xb8a8b7a1,0xb924b881,0xba1db96d,0xba41b9ba,0xbb32bab5,0xbb1ebab8,0xbbd6bb93,0xbbb3bb72,0xbbfebbf9,0xbbfabbe1,0xbba9bbe3,
0xae918000,0xb0108000,0xb4dbb288,0xb5f7b408,0xb7ddb665,0xb8c1b7cd,0xb946b8a0,0xba39b989,0xba64b9dc,0xbb4abad0,0xbb3dbad9,0xbbe2bba6,0xbbc8bb8c,0xbbf9bbfe,0xbbffbbee,0xbb8bbbd2,
0xaec38000,0xb0298000,0xb4ffb2b9,0xb61ab420,0xb80ab693,0xb8dbb7f9,0xb966b8bf,0xba54b9a4,0xba85b9fe,0xbb60bae9,0xbb59baf9,0xbbedbbb7,0xbbd9bba4,0xbbf0bc00,0xbc00bbf8,0xbb6abbbe,
0xaef58000,0xb0428000,0xb523b2ea,0xb63cb438,0xb825b6c1,0xb8f3b812,0xb986b8dd,0xba6fb9be,0xbaa5ba1f,0xbb76bb02,0xbb73bb17,0xbbf5bbc7,0xbbe7bbb9,0xbbe4bbff,0xbbfcbbfe,0xbb45bba6,
0xaf278000,0xb05b8000,0xb546b31b,0xb65fb451,0xb840b6ee,0xb90cb828,0xb9a6b8fb,0xba89b9d8,0xbac4ba3f,0xbb89bb1a,0xbb8bbb33,0xbbfbbbd5,0xbbf2bbcb,0xbbd6bbfb,0xbbf4bc00,0xbb1bbb8a,
0xaf598000,0xb0748000,0xb56ab34c,0xb682b469,0xb85ab71b,0xb924b83d,0xb9c5b918,0xbaa2b9f2,0xbae1ba5e,0xbb9cbb30,0xbba1bb4e,0xbbffbbe1,0xbbfabbdb,0xbbc3bbf5,0xbbe7bbfe,0xbaeebb6b,
0xaf8b8000,0xb08d8000,0xb58db37d,0xb6a4b481,0xb874b748,0xb93cb852,0xb9e3b935,0xbababa0b,0xbafeba7c,0xbbacbb46,0xbbb5bb67,0xbc00bbeb,0xbbffbbe8,0xbbaebbec,0xbbd7bbf9,0xbabdbb49,
0xafbd8000,0xb0a68000,0xb5b1b3ae,0xb6c6b499,0xb88eb775,0xb954b867,0xba00b951,0xbad1ba23,0xbb18ba99,0xbbbcbb5a,0xbbc6bb7d,0xbbffbbf3,0xbc00bbf2,0xbb96bbe0,0xbbc2bbf0,0xba89bb22,
0xb0be8000,0xb1858000,0xb6e8b4b1,0xb7f3b570,0xb96bb87c,0xba19b91d,0xbae8ba3b,0xbb7fbae6,0xbbc9bb6e,0xbc00bbdd,0xbbfcbbf9,0xbb8ebbe5,0xbb7abbd1,0xba35bafc,0xba50baf9,0xb820b93e,
0xb0d78000,0xb19e8000,0xb70ab4c9,0xb80ab587,0xb982b891,0xba2db930,0xbafeba52,0xbb8ebaf9,0xbbd6bb80,0xbc00bbe6,0xbbf6bbfd,0xbb76bbda,0xbb5cbbc0,0xba00bad6,0xba15bacc,0xb79bb8fb,
0xb0f08000,0xb1b68000,0xb72cb4e1,0xb81ab59f,0xb999b8a6,0xba41b943,0xbb13ba69,0xbb9cbb0b,0xbbe0bb91,0xbbfebbed,0xbbeebc00,0xbb5cbbcd,0xbb3abbab,0xb9c9baae,0xb9d6ba9c,0xb6f4b8b5,
0xb1098000,0xb1cf8000,0xb74eb4f9,0xb82ab5b6,0xb9afb8ba,0xba54b956,0xbb27ba7f,0xbba9bb1d,0xbbe9bba0,0xbbfbbbf4,0xbbe3bc00,0xbb3fbbbe,0xbb16bb95,0xb990ba83,0xb994ba69,0xb648b86d,
0xb1228000,0xb1e88000,0xb76fb511,0xb83ab5ce,0xb9c5b8ce,0xba67b969,0xbb3aba95,0xbbb5bb2e,0xbbf1bbaf,0xbbf6bbf8,0xbbd7bbfe,0xbb21bbad,0xbaeebb7b,0xb954ba56,0xb94fba33,0xb599b822,
0xb13b8000,0xb2018000,0xb790b529,0xb84ab5e5,0xb9dab8e2,0xba7ab97b,0xbb4cbaaa,0xbbc0bb3e,0xbbf7bbbc,0xbbefbbfc,0xbbc8bbfb,0xbb01bb9b,0xbac4bb5f,0xb916ba27,0xb907b9fa,0xb4e7b7ac,
0xb1538000,0xb2198000,0xb7b2b540,0xb85ab5fd,0xb9f0b8f6,0xba8cb98d,0xbb5ebabf,0xbbcbbb4e,0xbbfcbbc9,0xbbe7bbff,0xbbb7bbf6,0xbadebb86,0xba97bb41,0xb8d6b9f6,0xb8bcb9be,0xb432b710,
0xb16c8000,0xb2328000,0xb7d2b558,0xb86ab614,0xba04b909,0xba9eb99f,0xbb6fbad3,0xbbd4bb5d,0xbbfebbd4,0xbbdebc00,0xbba3bbee,0xbababb70,0xba67bb20,0xb894b9c3,0xb86fb980,0xb2f7b670,
0x98b69248,0xa901a2ad,0x9d7f9bdb,0xadd5ac2b,0xa0529f12,0xb093af7e,0xa1e4a11b,0xb238b166,0xa376a2ad,0xb3d9b309,0xa484a420,0xb4bab454,0xa54da4e9,0xb584b520,0xa616a5b2,0xb64bb5e8,
0x9f1298b6,0xa998a376,0xa420a1e4,0xae84aca9,0xa67ba54d,0xb11cb02f,0xa86ba7a8,0xb2f0b207,0xa998a901,0xb460b3d9,0xaac5aa2f,0xb543b4d2,0xabf2ab5c,0xb622b5b3,0xac90ac44,0xb6fcb690,
0xa1e49bdb,0xaa2fa420,0xa6dfa4e9,0xaf33ad26,0xa966a86b,0xb1a4b09f,0xab5caa61,0xb3a8b2a7,0xaca9ac2b,0xb4d2b454,0xada3ad26,0xb5cbb54f,0xae9dae20,0xb6beb645,0xaf97af1a,0xb7a9b734,
0xa4209d7f,0xaac5a484,0xa8cfa6df,0xafe2ada3,0xab8eaa2f,0xb22cb10f,0xad26ac77,0xb42fb346,0xae84add5,0xb543b4ba,0xafe2af33,0xb651b5cb,0xb09fb048,0xb756b6d4,0xb14db0f6,0xb829b7d5,
0xa54d9f12,0xab5ca4e9,0xaa2fa86b,0xb048ae20,0xacdbabf2,0xb2b3b17f,0xae9dadbc,0xb48ab3e5,0xb02faf7e,0xb5b3b520,0xb10fb09f,0xb6d4b645,0xb1eeb17f,0xb7ebb761,0xb2ccb25d,0xb87bb839,
0xa67ba052,0xabf2a54d,0xab8ea966,0xb09fae9d,0xadeeacdb,0xb33ab1ee,0xb00aaf01,0xb4e4b441,0xb11cb093,0xb622b584,0xb22cb1a4,0xb756b6be,0xb33ab2b3,0xb83eb7eb,0xb423b3c0,0xb8cab885,
0xa7a8a11b,0xac44a5b2,0xac77aa61,0xb0f6af1a,0xaf01adbc,0xb3c0b25d,0xb0c5b023,0xb53db490,0xb207b166,0xb690b5e8,0xb346b2a7,0xb7d5b734,0xb441b3e5,0xb885b839,0xb4deb490,0xb917b8cf,
0xa86ba1e4,0xac90a616,0xad26ab5c,0xb14daf97,0xb00aae9d,0xb423b2cc,0xb17fb0c5,0xb596b4de,0xb2f0b238,0xb6fcb64b,0xb42fb3a8,0xb829b7a9,0xb4e4b48a,0xb8cab87b,0xb596b53d,0xb961b917,
0xacdba67b,0xaf33a8cf,0xb1a4b00a,0xb429b1fa,0xb466b33a,0xb66db54f,0xb5eeb52c,0xb846b783,0xb767b6ad,0xb93db8c5,0xb866b80e,0xba16b9ae,0xb90db8bb,0xbacbba75,0xb9a7b95c,0xbb5abb18,
0xad26a6df,0xaf7ea901,0xb1fab048,0xb454b238,0xb4a8b3a8,0xb6adb584,0xb645b579,0xb86eb7ca,0xb7d0b70d,0xb96ab8f0,0xb8a2b846,0xba44b9db,0xb94eb8fa,0xbaf7baa2,0xb9eab99e,0xbb7ebb40,
0xad71a744,0xafc9a934,0xb251b086,0xb47eb276,0xb4eab40b,0xb6ebb5b9,0xb69bb5c5,0xb895b809,0xb81cb76c,0xb995b919,0xb8dcb87e,0xba70ba08,0xb98cb936,0xbb1fbacd,0xba2ab9de,0xbb9ebb65,
0xadbca7a8,0xb00aa966,0xb2a7b0c5,0xb4a8b2b3,0xb52cb441,0xb729b5ee,0xb6f1b611,0xb8bbb82c,0xb84eb7ca,0xb9bfb942,0xb914b8b4,0xba9aba32,0xb9c8b971,0xbb44baf5,0xba66ba1a,0xbbbabb86,
0xae07a806,0xb02fa998,0xb2fdb103,0xb4d2b2f0,0xb56db478,0xb767b622,0xb745b65c,0xb8e1b84e,0xb880b813,0xb9e8b96a,0xb94bb8e8,0xbac1ba5b,0xba01b9a9,0xbb66bb1b,0xba9fba53,0xbbd1bba3,
0xae52a839,0xb055a9ca,0xb352b141,0xb4fcb32e,0xb5aeb4ae,0xb7a4b656,0xb799b6a7,0xb906b871,0xb8b1b841,0xba10b991,0xb981b91c,0xbae7ba82,0xba38b9e0,0xbb85bb3d,0xbad4ba8a,0xbbe3bbbc,
0xae9da86b,0xb07aa9fd,0xb3a8b17f,0xb526b36b,0xb5eeb4e4,0xb7e0b68a,0xb7ebb6f1,0xb92ab892,0xb8e1b86e,0xba36b9b7,0xb9b4b94e,0xbb0abaa8,0xba6cba14,0xbba0bb5d,0xbb04babc,0xbbf1bbd1,
0xaee8a89d,0xb09faa2f,0xb3fdb1bd,0xb54fb3a8,0xb62eb51a,0xb80eb6be,0xb81eb73a,0xb94eb8b4,0xb910b89a,0xba5bb9db,0xb9e6b97e,0xbb2cbacb,0xba9dba46,0xbbb8bb7b,0xbb31baec,0xbbfbbbe3,
0xb0c5aa61,0xb1eeabf2,0xb579b3e5,0xb6beb4e4,0xb82cb6f1,0xb90db83e,0xb971b8d4,0xba6cb9c8,0xba7fb9ff,0xbb66baf7,0xbb4bbaed,0xbbebbbb8,0xbbcdbb95,0xbbf4bc00,0xbbffbbf0,0xbb80bbca,
0xb0eaaa93,0xb213ac12,0xb5a2b411,0xb6e5b502,0xb849b724,0xb928b856,0xb993b8f5,0xba88b9e4,0xbaa1ba22,0xbb7cbb10,0xbb67bb0d,0xbbf4bbc8,0xbbdebbad,0xbbeabc00,0xbbffbbf9,0xbb5cbbb3,
0xb10faac5,0xb238ac2b,0xb5cbb42f,0xb70db520,0xb866b756,0xb942b86e,0xb9b4b914,0xbaa2b9ff,0xbac1ba44,0xbb90bb29,0xbb81bb2c,0xbbfbbbd6,0xbbebbbc1,0xbbdbbbfc,0xbbfbbbff,0xbb34bb98,
0xb134aaf8,0xb25dac44,0xb5f4b44e,0xb734b53d,0xb883b788,0xb95cb885,0xb9d5b934,0xbabcba1a,0xbae1ba65,0xbba3bb40,0xbb99bb48,0xbbffbbe3,0xbbf6bbd3,0xbbcabbf6,0xbbf2bc00,0xbb07bb7a,
0xb15aab2a,0xb282ac5e,0xb61db46c,0xb75cb55b,0xb89fb7ba,0xb975b89d,0xb9f5b953,0xbad5ba34,0xbafeba84,0xbbb4bb56,0xbbafbb62,0xbc00bbed,0xbbfcbbe2,0xbbb5bbed,0xbbe4bbfd,0xbad7bb57,
0xb17fab5c,0xb2a7ac77,0xb645b48a,0xb783b579,0xb8bbb7eb,0xb98eb8b4,0xba14b971,0xbaedba4e,0xbb1bbaa2,0xbbc3bb6b,0xbbc1bb7b,0xbbffbbf5,0xbc00bbee,0xbb9cbbe1,0xbbd2bbf6,0xbaa2bb31,
0xb1a4ab8e,0xb2ccac90,0xb66db4a8,0xb7a9b596,0xb8d7b80e,0xb9a7b8ca,0xba32b98e,0xbb04ba66,0xbb35bac0,0xbbd1bb7e,0xbbd2bb91,0xbbfbbbfb,0xbbffbbf7,0xbb80bbd2,0xbbbbbbeb,0xba6abb07,
0xb1c9abc0,0xb2f0aca9,0xb696b4c6,0xb7d0b5b3,0xb8f2b826,0xb9bfb8e1,0xba4fb9ab,0xbb1bba7f,0xbb4ebadc,0xbbddbb90,0xbbe0bba6,0xbbf5bbfe,0xbbfcbbfd,0xbb61bbc0,0xbba0bbdd,0xba2ebada,
0xb315acc2,0xb41dad8a,0xb7f6b5d1,0xb890b6b8,0xb9d7b8f7,0xba86b9a0,0xbb30ba96,0xbbb5bb39,0xbbe7bba1,0xbbfabbf6,0xbbecbc00,0xbb4cbbc1,0xbb3fbbab,0xb9bfba9f,0xb9efbaa9,0xb707b8b4,
0xb33aacdb,0xb42fada3,0xb80eb5ee,0xb8a2b6d4,0xb9efb90d,0xba9ab9b4,0xbb44baad,0xbbc1bb4b,0xbbefbbb0,0xbbf5bbfb,0xbbe0bbff,0xbb2dbbaf,0xbb19bb93,0xb983ba72,0xb9abba75,0xb656b869,
0xb35facf4,0xb441adbc,0xb821b60b,0xb8b4b6f1,0xba05b923,0xbaadb9c8,0xbb57bac3,0xbbcdbb5b,0xbbf6bbbe,0xbbeebbfe,0xbbd3bbfd,0xbb0cbb9c,0xbaf0bb78,0xb944ba42,0xb965ba3e,0xb5a2b81c,
0xb383ad0d,0xb454add5,0xb834b628,0xb8c5b70d,0xba1cb939,0xbac0b9db,0xbb69bad9,0xbbd6bb6b,0xbbfbbbcb,0xbbe5bc00,0xbbc2bbf8,0xbae9bb87,0xbac5bb5b,0xb903ba10,0xb91cba03,0xb4eab799,
0xb3a8ad26,0xb466adee,0xb846b645,0xb8d7b729,0xba32b94e,0xbad2b9ef,0xbb7bbaed,0xbbdfbb7a,0xbbfebbd6,0xbbdabc00,0xbbafbbf1,0xbac3bb6f,0xba96bb3b,0xb8c0b9db,0xb8cfb9c6,0xb42fb6f6,
0xb3cdad3f,0xb478ae07,0xb859b662,0xb8e8b745,0xba48b963,0xbae4ba01,0xbb8bbb01,0xbbe7bb88,0xbc00bbe0,0xbbcebbff,0xbb9abbe8,0xba9bbb56,0xba65bb18,0xb87bb9a5,0xb880b985,0xb2e4b651,
0xb3f1ad58,0xb48aae20,0xb86bb67f,0xb8fab761,0xba5db978,0xbaf5ba14,0xbb9abb15,0xbbeebb95,0xbc00bbe9,0xbbc0bbfc,0xbb82bbdd,0xba72bb3b,0xba30baf2,0xb834b96c,0xb82eb942,0xb166b5a8,
0xb40bad71,0xb49cae39,0xb87eb69b,0xb90bb77d,0xba72b98c,0xbb06ba26,0xbba8bb27,0xbbf4bba2,0xbbfebbf0,0xbbb0bbf9,0xbb68bbd0,0xba46bb1d,0xb9f9baca,0xb7d5b931,0xb7b4b8fc,0xafc9b4fc,
0x39b839ba,0x3a973ab5,0x39b339b5,0x3a583a78,0x39af39b1,0x3a153a37,0x39aa39ad,0x39cd39f2,0x39a639a8,0x398239a8,0x39a139a4,0x3933395b,0x399d399f,0x38e03909,0x3999399b,0x388938b5,
0xb979b972,0xb865b832,0xb986b980,0xb8c7b896,0xb994b98d,0xb924b8f6,0xb9a1b99b,0xb97db951,0xb9afb9a8,0xb9d2b9a8,0xb9bcb9b5,0xba21b9fa,0xb9c9b9c3,0xba6bba47,0xb9d6b9d0,0xbab0ba8e,
0xb9f4b9fe,0xbac7bae9,0xb9dfb9e9,0xba7ebaa3,0xb9c9b9d4,0xba2dba56,0xb9b3b9be,0xb9d6ba02,0xb99db9a8,0xb979b9a8,0xb986b992,0xb916b948,0xb970b97b,0xb8adb8e2,0xb958b964,0xb840b877,
0x39373927,0x381a37b7,0x39583948,0x38943858,0x39793969,0x390738ce,0x39993989,0x3974393e,0x39b839a8,0x39da39a8,0x39d639c7,0x3a393a0b,0x39f439e5,0x3a903a65,0x3a113a02,0x3ade3ab8,
0x3a2d3a3f,0x3af43b1a,0x3a093a1b,0x3aa23acc,0x39e339f6,0x3a453a74,0x39bc39d0,0x39df3a13,0x399439a8,0x397039a8,0x396b3980,0x38f83935,0x39413956,0x387a38ba,0x3916392b,0x37e83838,
0xb8f3b8d8,0xb79bb705,0xb929b90e,0xb85fb817,0xb95db943,0xb8eab8a6,0xb990b976,0xb96bb92b,0xb9c0b9a8,0xb9e3b9a8,0xb9f0b9d8,0xba50ba1b,0xba1dba07,0xbab3ba83,0xba49ba33,0xbb0abae0,
0xba64ba7c,0xbb1ebb46,0xba31ba4b,0xbac4baf3,0xb9fcba17,0xba5cba92,0xb9c5b9e1,0xb9e7ba23,0xb98bb9a8,0xb966b9a8,0xb94fb96d,0xb8dbb922,0xb911b930,0xb845b891,0xb8d1b8f1,0xb74eb7ee,
0x38ad3887,0x36ff364e,0x38f838d3,0x382a37ac,0x3941391d,0x38cc387c,0x39863964,0x39623918,0x39c939a8,0x39eb39a8,0x3a0939e9,0x3a673a2b,0x3a453a27,0x3ad53aa0,0x3a7e3a62,0x3b323b05,
0x3b453b6e,0x3bbc3bdd,0x3ae53b17,0x3b573b8f,0x3a733aae,0x3ac73b14,0x39f03a33,0x3a113a71,0x395d39a8,0x393739a8,0x38bc390e,0x384038bf,0x380f3867,0x365f3775,0x36af376a,0x341a3540,
0xb65fb593,0xb389b115,0xb7e8b726,0xb625b4f9,0xb8adb852,0xb830b748,0xb958b905,0xb933b8b5,0xb9f4b9a8,0xba15b9a8,0xba7eba3b,0xbad1ba78,0xbaf4babc,0xbb63bb20,0xbb57bb28,0xbbc6bb9b,
0xbb68bb91,0xbbd0bbed,0xbb04bb39,0xbb6fbba6,0xba89bac9,0xbadbbb2b,0xb9f8ba43,0xba19ba7f,0xb954b9a8,0xb92eb9a8,0xb89eb8fb,0xb820b8ab,0xb7b2b83d,0xb5ebb71b,0xb60eb6e3,0xb2deb4b1,
0x35bc34d5,0x32322f0e,0x377a369e,0x35b13469,0x388e3828,0x380f36ee,0x394f38f1,0x392938a0,0x39fc39a8,0x3a1d39a8,0x3a933a4b,0x3ae53a87,0x3b133ad6,0x3b7a3b36,0x3b783b49,0x3bd93bb1,
0x3b873baf,0x3be13bf8,0x3b213b58,0x3b853bbb,0x3a9e3ae3,0x3aee3b41,0x3a003a52,0x3a213a8e,0x394a39a8,0x392439a8,0x387f38e7,0x37fe3896,0x37423812,0x357636c1,0x356a3659,0x31853420,
0xb517b414,0xb0d7abd9,0xb70ab614,0xb53ab3ae,0xb86fb7f9,0xb7ddb693,0xb946b8dd,0xb91fb88c,0xba04b9a8,0xba25b9a8,0xbaa9ba5a,0xbaf7ba95,0xbb2fbaf0,0xbb90bb4b,0xbb96bb67,0xbbe8bbc4,
0xbba3bbc9,0xbbefbbff,0xbb3dbb74,0xbb9abbcd,0xbab3bafc,0xbb01bb55,0xba09ba62,0xba29ba9c,0xb941b9a8,0xb91bb9a8,0xb85fb8d3,0xb7bdb881,0xb6d2b7cd,0xb4ffb665,0xb4c3b5ce,0xb029b31b,
0x346f32a1,0x2ef52248,0x36993587,0x34c33288,0x385037a1,0x379b3637,0x393c38c9,0x39163877,0x3a0d39a8,0x3a2d39a8,0x3abd3a69,0x3b0a3aa3,0x3b4a3b08,0x3ba33b5f,0x3bb03b82,0x3bf43bd5,
0x3bf83c00,0x3bf93bd4,0x3bac3bdc,0x3be43bfe,0x3b133b69,0x3b543bab,0x3a313aaa,0x3a503ae0,0x391139a8,0x38ea39a8,0x377a386d,0x366b3817,0x34873608,0x313b348d,0x2d9731f4,0xad65291b,
0xac3828b6,0x2ec33365,0xb44bb160,0xb0bea57f,0xb759b5da,0xb648b45d,0xb90cb862,0xb8e5b80d,0xba35b9a8,0xba54b9a8,0xbb1bbab1,0xbb5cbae6,0xbbb5bb72,0xbbe9bbb2,0xbbfcbbe3,0xbbf5bc00,
0xbbfebbfc,0xbbefbbbc,0xbbbdbbe9,0xbbeebc00,0xbb24bb7b,0xbb63bbb9,0xba39bab8,0xba58baed,0xb907b9a8,0xb8e0b9a8,0xb737b858,0xb625b802,0xb40eb5ab,0xb042b42c,0xa9b1b0cb,0x30109a48,
0x25e4ad7e,0xb0beb475,0x33a23036,0x2f8ba3db,0x3715357c,0x360233f7,0x3902384d,0x38db37ee,0x3a3d39a8,0x3a5c39a8,0x3b2c3abf,0x3b6a3af3,0x3bc53b84,0x3bf23bc0,0x3bff3bee,0x3be93c00,
0x3c003bf4,0x3be23ba0,0x3bcc3bf3,0x3bf53bff,0x3b353b8c,0x3b713bc6,0x3a413ac6,0x3a603af9,0x38fd39a8,0x38d639a8,0x36f43842,0x35df37d8,0x3328354c,0x2e913396,0x16482f40,0xb16ca852,
0x251b304e,0x32193534,0xb2adae14,0xad972aac,0xb6d2b51d,0xb5bcb334,0xb8f8b838,0xb8d1b7c2,0xba45b9a8,0xba64b9a8,0xbb3dbacc,0xbb78baff,0xbbd3bb95,0xbbf8bbcb,0xbc00bbf7,0xbbdabbfd,
0xbbfebbe6,0xbbd2bb80,0xbbd9bbfa,0xbbfbbbfb,0xbb45bb9d,0xbb7fbbd1,0xba49bad3,0xba67bb05,0xb8f3b9a8,0xb8ccb9a8,0xb6afb82d,0xb599b7ac,0xb232b4ed,0xac9cb2d2,0x294dace7,0x32c62c83,
0xac06b1db,0xb371b5f1,0x31b62b75,0x2b43adb0,0x368d34bd,0x3576326f,0x38ee3822,0x38c73796,0x3a4d39a8,0x3a6b39a8,0x3b4c3ad9,0x3b853b0b,0x3bdf3ba4,0x3bfd3bd6,0x3bfc3bfd,0x3bc83bf8,
0x3bbd3b5a,0x3b473a99,0x3bfe3bf4,0x3bf93bbe,0x3b8b3bdb,0x3bb83bf7,0x3a6f3b11,0x3a8c3b3e,0x38c139a8,0x389939a8,0x35523780,0x343236cc,0x294d320d,0xad332de2,0xb40eaedc,0xb6a4b408,
0x346336aa,0x36f438b0,0xa6ad3004,0x2e2d3451,0xb52fb1aa,0xb40ead1a,0xb8bcb76a,0xb894b6b5,0xba73b9a8,0xba90b9a8,0xbb92bb17,0xbbbdbb43,0xbbffbbe0,0xbbf6bbf9,0xbbb2bbf0,0xbb35bbb4,
0xbba5bb30,0xbb21ba5e,0xbc00bbeb,0xbbf3bbaa,0xbb98bbe4,0xbbc2bbfb,0xba76bb1d,0xba93bb49,0xb8b7b9a8,0xb88eb9a8,0xb50bb753,0xb3d3b69e,0xa17fb147,0x2f27ac51,0x34b73099,0x37423499,
0xb50bb75e,0xb790b900,0x9cb6b12e,0xb010b4e1,0x34e730e4,0x33892b11,0x38b2373d,0x38893687,0x3a7a39a8,0x3a9739a8,0x3b9e3b22,0x3bc63b4e,0x3c003be8,0x3bef3bfd,0x3b983be5,0x3b0d3b9e,
0x3b893b02,0x3af73a1f,0x3c003bdf,0x3beb3b93,0x3ba33bec,0x3bcb3bfe,0x3a7e3b28,0x3a9b3b53,0x38ad39a8,0x388439a8,0x34c33726,0x33403670,0xa51b3080,0xb08d297f,0xb55eb1c3,0xb7ddb529,
0x35b13807,0x3815394d,0x28843257,0x31093570,0xb49fb01d,0xb2f7a7da,0xb8a8b710,0xb87fb659,0xba81b9a8,0xba9eb9a8,0xbba9bb2e,0xbbcfbb58,0xbbffbbef,0xbbe6bbff,0xbb7abbd7,0xbae1bb86,
0xbb6abad0,0xbacbb9dc,0xbbfdbbd0,0xbbe1bb79,0xbbaebbf2,0xbbd3bc00,0xba85bb33,0xbaa2bb5d,0xb8a3b9a8,0xb87ab9a8,0xb47bb6f9,0xb2adb642,0x2a7aaf72,0x3185a4b6,0x360232ea,0x383a35b6,
0xb654b85d,0xb85fb996,0xac38b37d,0xb201b5fd,0x34572eaa,0x32631e48,0x389e36e3,0x3874362b,0x3a8939a8,0x3aa539a8,0x3bb33b39,0x3bd73b62,0x3bfc3bf5,0x3bdc3c00,0x3b593bc7,0x3ab33b6b,
0x39b739b9,0x3a883aa6,0x39b239b4,0x3a483a68,0x39ae39b0,0x3a033a26,0x39a939ab,0x39bb39e0,0x39a539a7,0x396e3995,0x39a039a3,0x391e3947,0x399c399e,0x38ca38f5,0x3997399a,0x3873389f,
0xb97cb975,0xb87eb84c,0xb98ab983,0xb8deb8ae,0xb997b991,0xb93bb90d,0xb9a5b99e,0xb993b967,0xb9b2b9ab,0xb9e6b9bd,0xb9bfb9b9,0xba34ba0e,0xb9ccb9c6,0xba7dba59,0xb9d9b9d3,0xbac0ba9f,
0xb9efb9f9,0xbab6bad9,0xb9d9b9e4,0xba6aba91,0xb9c4b9cf,0xba18ba42,0xb9aeb9b9,0xb9bfb9ec,0xb997b9a3,0xb961b991,0xb981b98c,0xb8fcb92f,0xb96ab975,0xb892b8c8,0xb953b95e,0xb824b85c,
0x3940392f,0x383937f6,0x39613950,0x38b13876,0x39813971,0x392338eb,0x39a03991,0x398e395a,0x39bf39b0,0x39f339c1,0x39de39cf,0x3a4f3a22,0x39fb39ec,0x3aa43a7b,0x3a183a0a,0x3af03acb,
0x3a243a36,0x3ae13b07,0x39ff3a12,0x3a8b3ab7,0x39d939ec,0x3a2c3a5d,0x39b239c6,0x39c439f9,0x398a399e,0x3953398c,0x39613975,0x38d93917,0x3936394b,0x3859389a,0x390b3921,0x37a43816,
0xb901b8e6,0xb7e6b750,0xb936b91c,0xb883b83c,0xb96ab950,0xb90bb8c8,0xb99cb983,0xb98ab94b,0xb9ccb9b4,0xb9ffb9c6,0xb9fbb9e4,0xba6aba36,0xba28ba12,0xbacaba9b,0xba53ba3e,0xbb1dbaf5,
0xba57ba70,0xbb09bb33,0xba24ba3e,0xbaabbadc,0xb9efba0a,0xba40ba77,0xb9b7b9d3,0xb9c8ba05,0xb97cb99a,0xb944b988,0xb940b95e,0xb8b6b8fe,0xb901b921,0xb81eb86b,0xb8c0b8e1,0xb6fcb79e,
0x38c0389a,0x375636a7,0x390b38e6,0x38543800,0x3953392f,0x38f238a4,0x39973975,0x3985393d,0x39d939b9,0x3a0c39ca,0x3a1839f9,0x3a843a4a,0x3a533a36,0x3aed3abb,0x3a8b3a70,0x3b473b1c,
0x3b2e3b5a,0x3ba63bce,0x3aca3afe,0x3b373b74,0x3a533a91,0x3a9d3aef,0x39cc3a12,0x39de3a42,0x39363983,0x38fc3971,0x389238e6,0x37fb3880,0x37c5383c,0x35d136eb,0x3651370d,0x330934ae,
0xb6c3b5fa,0xb460b251,0xb824b788,0xb6b8b590,0xb8d9b880,0xb873b7d5,0xb981b92f,0xb96eb8f5,0xba18b9cf,0xba48b9e0,0xba9dba5d,0xbafabaa6,0xbb0fbad9,0xbb80bb43,0xbb6cbb40,0xbbd8bbb2,
0xbb51bb7d,0xbbbdbbe0,0xbae7bb1f,0xbb4ebb8c,0xba66baa9,0xbaafbb04,0xb9d1ba1e,0xb9e2ba4e,0xb928b97e,0xb8edb96c,0xb86eb8cd,0xb7afb866,0xb74bb80b,0xb54fb684,0xb5a2b679,0xb197b411,
0x362e3549,0x338330de,0x37e6370d,0x3651350e,0x38c0385c,0x38593788,0x397c3921,0x396a38e6,0x3a2439d3,0x3a5339e4,0x3ab63a70,0x3b0f3ab7,0x3b2e3af5,0x3b973b5a,0x3b8d3b61,0x3be83bc7,
0x3b703b9c,0x3bd03bef,0x3b033b3d,0x3b653ba2,0x3a793ac1,0x3ac03b19,0x39d53a2a,0x39e63a59,0x3919397a,0x38de3967,0x384938b4,0x3761384c,0x36cf37b4,0x34cc361d,0x34f035e2,0x302332e4,
0xb596b496,0xb244aecf,0xb783b690,0xb5e8b48a,0xb8a7b836,0xb83eb73a,0xb978b912,0xb965b8d7,0xba30b9d7,0xba5fb9e8,0xbacdba82,0xbb23bac8,0xbb4cbb10,0xbbacbb6f,0xbbaabb7f,0xbbf4bbd8,
0xbb8dbbb7,0xbbe0bbf9,0xbb1dbb5a,0xbb7abbb5,0xba8bbad9,0xbad0bb2d,0xb9d9ba36,0xb9eaba65,0xb90bb975,0xb8cfb963,0xb824b89a,0xb713b831,0xb651b750,0xb447b5b3,0xb43bb549,0xad58b1a4,
0x34fc33c0,0x31032bc0,0x371e3611,0x357e3405,0x388d3811,0x382436eb,0x39733903,0x396138c8,0x3a3c39db,0x3a6a39ec,0x3ae43a94,0x3b373ad9,0x3b673b2a,0x3bbe3b83,0x3bc33b9a,0x3bfc3be7,
0x3bed3bff,0x3bff3bea,0x3b8d3bc7,0x3bcc3bf5,0x3ae13b40,0x3b1d3b83,0x39ef3a70,0x39ff3a9b,0x38c0395e,0x3883394b,0x36c33816,0x357e3750,0x33833549,0x2e84332e,0x28cf3061,0xb0aca5b2,
0xaf7ea376,0x29663166,0xb514b2fd,0xb2bfad71,0xb809b69b,0xb734b555,0xb95cb8b9,0xb949b87b,0xba75b9f1,0xbaa1ba01,0xbb49bae9,0xbb8bbb25,0xbbcfbb96,0xbbf9bbd2,0xbc00bbf2,0xbbe3bbfe,
0xbbf6bc00,0xbbfcbbda,0xbb9fbbd6,0xbbd8bbfb,0xbaf0bb52,0xbb2cbb92,0xb9f3ba7b,0xba03baa6,0xb8b1b95a,0xb873b947,0xb673b7f6,0xb52cb718,0xb276b4de,0xac5eb251,0x2052ae39,0x321f2bf2,
0x2cf4a806,0xad3fb2d8,0x34a831ee,0x31e22a93,0x37db364b,0x36fc3502,0x395738a9,0x3944386b,0x3a8039f5,0x3aab3a05,0x3b5b3af8,0x3b993b33,0x3bdd3ba7,0x3bfd3bdd,0x3bff3bfa,0x3bd13bf9,
0x3bfd3bfd,0x3bf53bc6,0x3baf3be3,0x3be23bff,0x3b003b64,0x3b393ba0,0x39f73a86,0x3a083ab0,0x38a23955,0x38633942,0x362237bf,0x34d836e0,0x31663472,0x286b3172,0xaaf82b5c,0xb390ae84,
0xa8cf2cf4,0x2fc93423,0xb43bb0de,0xb103a484,0xb7a4b5fa,0xb6c3b4ae,0xb953b89a,0xb940b85c,0xba8bb9f9,0xbab6ba0a,0xbb6cbb07,0xbba6bb40,0xbbe8bbb7,0xbc00bbe7,0xbbfabbff,0xbbbabbf1,
0xbc00bbf6,0xbbebbbae,0xbbbebbed,0xbbebbc00,0xbb0fbb74,0xbb47bbad,0xb9fbba91,0xba0cbabb,0xb892b950,0xb854b93d,0xb5d1b788,0xb484b6a7,0xb055b405,0x9248b093,0x2e6ba484,0x347e3086,
0x98b6afe2,0xb128b4d8,0x339c2f97,0x3023a420,0x376c35a8,0x368a345a,0x394e388b,0x393b384c,0x3a9639fd,0x3ac03a0e,0x3b7c3b16,0x3bb33b4d,0x3bf23bc5,0x3c003bef,0x3bf03c00,0x3ba03be5,
0x3bde3b91,0x3b8a3af7,0x3bf23bff,0x3c003be3,0x3b533bb9,0x3b823bdf,0x3a103ac5,0x3a203aec,0x38443939,0x38033925,0x342f366d,0x31b03584,0xa8392f65,0xb15a1d7f,0xb531b1c9,0xb7e0b55b,
0x3269358a,0x35a83819,0xae842a61,0x205231e2,0xb651b405,0xb567b15a,0xb936b83c,0xb923b7f6,0xbacaba12,0xbaf0ba22,0xbbbebb5a,0xbbe3bb88,0xbbfdbbf5,0xbbddbc00,0xbb81bbd6,0xbadfbb7c,
0xbbcebb70,0xbb6dbac6,0xbbf8bbfb,0xbbffbbd6,0xbb60bbc4,0xbb8dbbe7,0xba14bacf,0xba24baf5,0xb834b934,0xb7e6b921,0xb3b4b634,0xb103b549,0x2c44ada3,0x326925b2,0x35e23309,0x384135f4,
0xb3a8b63a,0xb63fb869,0x2cc2ad58,0xa89db2f0,0x3617335f,0x352c30ac,0x3931382c,0x391e37d5,0x3ad43a16,0x3afa3a26,0x3bc93b66,0x3bea3b92,0x3bf93bfa,0x3bcf3bff,0x3b5f3bc5,0x3aad3b5d,
0x3bba3b4c,0x3b4d3a93,0x3bfc3bf6,0x3bfd3bc7,0x3b6c3bce,0x3b973bed,0x3a183ad9,0x3a283afe,0x3824392f,0x37c5391c,0x330935fa,0x3055350e,0xae6b2bc0,0xb377aa61,0xb690b423,0xb890b68a,
0x347236e5,0x36d438b6,0xa9fd2f7e,0x2c1233fd,0xb5dcb2b3,0xb4f0affb,0xb92db81c,0xb919b7b4,0xbaddba1a,0xbb03ba2a,0xbbd3bb72,0xbbf0bb9c,0xbbf2bbfe,0xbbbfbbfc,0xbb38bbaf,0xba77bb3c,
0xbba4bb23,0xbb2aba5b,0xbbffbbee,0xbbfabbb6,0xbb77bbd7,0xbba1bbf3,0xba1cbae2,0xba2cbb07,0xb813b92a,0xb7a4b917,0xb25db5bf,0xaf4cb4d2,0x3048a839,0x34412cf4,0x373a34c0,0x38dc371e,
0xb50eb78e,0xb767b901,0x24e9b0d1,0xadd5b484,0x35a23207,0x34b42e9d,0x3928380b,0x39143793,0x3ae73a1e,0x3b0c3a2e,0x3bdb3b7d,0x3bf53ba6,0x3be93c00,0x3bad3bf7,0x3b0d3b97,0x3a3e3b18,
0xb999b996,0xb889b85d,0xb99db99b,0xb8e0b8b5,0xb9a1b99f,0xb933b909,0xb9a6b9a4,0xb982b95b,0xb9aab9a8,0xb9cdb9a8,0xb9afb9ad,0xba15b9f2,0xb9b3b9b1,0xba58ba37,0xb9b8b9b5,0xba97ba78,
0xb9d6b9dc,0xbab0bad0,0xb9c9b9d0,0xba6bba8e,0xb9bcb9c3,0xba21ba47,0xb9afb9b5,0xb9d2b9fa,0xb9a1b9a8,0xb97db9a8,0xb994b99b,0xb924b951,0xb986b98d,0xb8c7b8f6,0xb979b980,0xb865b896,
0x3958394d,0x38403807,0x39703964,0x38ad3877,0x3986397b,0x391638e2,0x399d3992,0x39793948,0x39b339a8,0x39d639a8,0x39c939be,0x3a2d3a02,0x39df39d4,0x3a7e3a56,0x39f439e9,0x3ac73aa3,
0x3a113a1f,0x3ade3b02,0x39f43a02,0x3a903ab8,0x39d639e5,0x3a393a65,0x39b839c7,0x39da3a0b,0x399939a8,0x397439a8,0x39793989,0x3907393e,0x39583969,0x389438ce,0x39373948,0x381a3858,
0xb916b900,0xb7e8b75e,0xb941b92b,0xb87ab838,0xb96bb956,0xb8f8b8ba,0xb994b980,0xb970b935,0xb9bcb9a8,0xb9dfb9a8,0xb9e3b9d0,0xba45ba13,0xba09b9f6,0xbaa2ba74,0xba2dba1b,0xbaf4bacc,
0xba49ba5e,0xbb0abb30,0xba1dba33,0xbab3bae0,0xb9f0ba07,0xba50ba83,0xb9c0b9d8,0xb9e3ba1b,0xb990b9a8,0xb96bb9a8,0xb95db976,0xb8eab92b,0xb929b943,0xb85fb8a6,0xb8f3b90e,0xb79bb817,
0x38d138b0,0x374e36aa,0x391138f1,0x384537ee,0x394f3930,0x38db3891,0x398b396d,0x39663922,0x39c539a8,0x39e739a8,0x39fc39e1,0x3a5c3a23,0x3a313a17,0x3ac43a92,0x3a643a4b,0x3b1e3af3,
0x3a7e3a99,0x3b323b5a,0x3a453a62,0x3ad53b05,0x3a093a27,0x3a673aa0,0x39c939e9,0x39eb3a2b,0x398639a8,0x396239a8,0x39413964,0x38cc3918,0x38f8391d,0x382a387c,0x38ad38d3,0x36ff37ac,
0xb6afb5f1,0xb41ab1db,0xb80fb76a,0xb65fb540,0xb8bcb867,0xb840b775,0xb95db90e,0xb937b8bf,0xb9f0b9a8,0xba11b9a8,0xba73ba33,0xbac7ba71,0xbae5baae,0xbb57bb14,0xbb45bb17,0xbbbcbb8f,
0xbb57bb80,0xbbc6bbe6,0xbaf4bb28,0xbb63bb9b,0xba7ebabc,0xbad1bb20,0xb9f4ba3b,0xba15ba78,0xb958b9a8,0xb933b9a8,0xb8adb905,0xb830b8b5,0xb7e8b852,0xb625b748,0xb65fb726,0xb389b4f9,
0x360e3534,0x32de304e,0x37b236e3,0x35eb34b1,0x389e383d,0x3820371b,0x395438fb,0x392e38ab,0x39f839a8,0x3a1939a8,0x3a893a43,0x3adb3a7f,0x3b043ac9,0x3b6f3b2b,0x3b683b39,0x3bd03ba6,
0x3b783ba0,0x3bd93bf4,0x3b133b49,0x3b7a3bb1,0x3a933ad6,0x3ae53b36,0x39fc3a4b,0x3a1d3a87,0x394f39a8,0x392939a8,0x388e38f1,0x380f38a0,0x377a3828,0x35b136ee,0x35bc369e,0x32323469,
0xb56ab475,0xb185ad7e,0xb742b659,0xb576b420,0xb87fb812,0xb7feb6c1,0xb94ab8e7,0xb924b896,0xba00b9a8,0xba21b9a8,0xba9eba52,0xbaeeba8e,0xbb21bae3,0xbb85bb41,0xbb87bb58,0xbbe1bbbb,
0xbb96bbbc,0xbbe8bbfc,0xbb2fbb67,0xbb90bbc4,0xbaa9baf0,0xbaf7bb4b,0xba04ba5a,0xba25ba95,0xb946b9a8,0xb91fb9a8,0xb86fb8dd,0xb7ddb88c,0xb70ab7f9,0xb53ab693,0xb517b614,0xb0d7b3ae,
0x34c33365,0x302928b6,0x36d235ce,0x34ff331b,0x385f37cd,0x37bd3665,0x394138d3,0x391b3881,0x3a0939a8,0x3a2939a8,0x3ab33a62,0x3b013a9c,0x3b3d3afc,0x3b9a3b55,0x3ba33b74,0x3bef3bcd,
0x3bb03bd4,0x3bf43c00,0x3b4a3b82,0x3ba33bd5,0x3abd3b08,0x3b0a3b5f,0x3a0d3a69,0x3a2d3aa3,0x393c39a8,0x391639a8,0x385038c9,0x379b3877,0x369937a1,0x34c33637,0x346f3587,0x2ef53288,
0xad972248,0x2d6532a1,0xb487b1f4,0xb13ba91b,0xb77ab608,0xb66bb48d,0xb911b86d,0xb8eab817,0xba31b9a8,0xba50b9a8,0xbb13baaa,0xbb54bae0,0xbbacbb69,0xbbe4bbab,0xbbf8bbdc,0xbbf9bbfe,
0xbbfcbbff,0xbbf5bbc9,0xbbb5bbe3,0xbbe9bc00,0xbb1bbb72,0xbb5cbbb2,0xba35bab1,0xba54bae6,0xb90cb9a8,0xb8e5b9a8,0xb759b862,0xb648b80d,0xb44bb5da,0xb0beb45d,0xac38b160,0x2ec3a57f,
0x29b1abd9,0xb010b414,0x340e30cb,0x30421a48,0x373735ab,0x3625342c,0x39073858,0x38e03802,0x3a3939a8,0x3a5839a8,0x3b243ab8,0x3b633aed,0x3bbd3b7b,0x3bee3bb9,0x3bfe3be9,0x3bef3c00,
0x3bff3bf8,0x3be93baf,0x3bc53bee,0x3bf23c00,0x3b2c3b84,0x3b6a3bc0,0x3a3d3abf,0x3a5c3af3,0x390239a8,0x38db39a8,0x3715384d,0x360237ee,0x33a2357c,0x2f8b33f7,0x25e43036,0xb0bea3db,
0x96482f0e,0x316c34d5,0xb328af40,0xae912852,0xb6f4b54c,0xb5dfb396,0xb8fdb842,0xb8d6b7d8,0xba41b9a8,0xba60b9a8,0xbb35bac6,0xbb71baf9,0xbbccbb8c,0xbbf5bbc6,0xbc00bbf3,0xbbe2bbff,
0xbc00bbed,0xbbdabb91,0xbbd3bbf7,0xbbf8bbfd,0xbb3dbb95,0xbb78bbcb,0xba45bacc,0xba64baff,0xb8f8b9a8,0xb8d1b9a8,0xb6d2b838,0xb5bcb7c2,0xb2adb51d,0xad97b334,0x251bae14,0x32192aac,
0xa94db115,0xb2c6b593,0x32322ce7,0x2c9cac83,0x36af34ed,0x359932d2,0x38f3382d,0x38cc37ac,0x3a4939a8,0x3a6739a8,0x3b453ad3,0x3b7f3b05,0x3bd93b9d,0x3bfb3bd1,0x3bfe3bfa,0x3bd23bfb,
0x3bfc3bdd,0x3bc83b6e,0x3bdf3bfd,0x3bfd3bf8,0x3b4c3ba4,0x3b853bd6,0x3a4d3ad9,0x3a6b3b0b,0x38ee39a8,0x38c739a8,0x368d3822,0x35763796,0x31b634bd,0x2b43326f,0xac062b75,0xb371adb0,
0x340e364e,0x36a43887,0xa94d2edc,0x2d333408,0xb552b20d,0xb432ade2,0xb8c1b780,0xb899b6cc,0xba6fb9a8,0xba8cb9a8,0xbb8bbb11,0xbbb8bb3e,0xbbfebbdb,0xbbf9bbf7,0xbbbdbbf4,0xbb47bbbe,
0xbbb2bb46,0xbb35ba7c,0xbbffbbf0,0xbbf6bbb4,0xbb92bbe0,0xbbbdbbf9,0xba73bb17,0xba90bb43,0xb8bcb9a8,0xb894b9a8,0xb52fb76a,0xb40eb6b5,0xa6adb1aa,0x2e2dad1a,0x34633004,0x36f43451,
0xb4b7b705,0xb742b8d8,0x217fb099,0xaf27b499,0x350b3147,0x33d32c51,0x38b73753,0x388e369e,0x3a7639a8,0x3a9339a8,0x3b983b1d,0x3bc23b49,0x3c003be4,0x3bf33bfb,0x3ba53beb,0x3b213baa,
0x3b983b1a,0x3b0d3a3f,0x3c003be5,0x3bef3b9e,0x3b9e3be8,0x3bc63bfd,0x3a7a3b22,0x3a973b4e,0x38b239a8,0x388939a8,0x34e7373d,0x33893687,0x9cb630e4,0xb0102b11,0xb50bb12e,0xb790b4e1,
0x355e37b7,0x37dd3927,0x251b31c3,0x308d3529,0xb4c3b080,0xb340a97f,0xb8adb726,0xb884b670,0xba7eb9a8,0xba9bb9a8,0xbba3bb28,0xbbcbbb53,0xbc00bbec,0xbbebbbfe,0xbb89bbdf,0xbaf7bb93,
0xbb7abae9,0xbae1b9fe,0xbbffbbd7,0xbbe6bb86,0xbba9bbef,0xbbcfbbff,0xba81bb2e,0xba9ebb58,0xb8a8b9a8,0xb87fb9a8,0xb49fb710,0xb2f7b659,0x2884b01d,0x3109a7da,0x35b13257,0x38153570,
0xb602b832,0xb83ab972,0xaa7ab2ea,0xb185b5b6,0x347b2f72,0x32ad24b6,0x38a336f9,0x387a3642,0x3a8539a8,0x3aa239a8,0x3bae3b33,0x3bd33b5d,0x3bfd3bf2,0x3be13c00,0x3b6a3bd0,0x3acb3b79,
0x3b593ab5,0x3ab339ba,0x3bfc3bc7,0x3bdc3b6b,0x3bb33bf5,0x3bd73c00,0x3a893b39,0x3aa53b62,0x389e39a8,0x387439a8,0x345736e3,0x3263362b,0xac382eaa,0xb2011e48,0xb654b37d,0xb85fb5fd,
0xb99ab997,0xb89fb873,0xb99eb99c,0xb8f5b8ca,0xb9a3b9a0,0xb947b91e,0xb9a7b9a5,0xb995b96e,0xb9abb9a9,0xb9e0b9bb,0xb9b0b9ae,0xba26ba03,0xb9b4b9b2,0xba68ba48,0xb9b9b9b7,0xbaa6ba88,
0xb9d3b9d9,0xba9fbac0,0xb9c6b9cc,0xba59ba7d,0xb9b9b9bf,0xba0eba34,0xb9abb9b2,0xb9bdb9e6,0xb99eb9a5,0xb967b993,0xb991b997,0xb90db93b,0xb983b98a,0xb8aeb8de,0xb975b97c,0xb84cb87e,
0x395e3953,0x385c3824,0x3975396a,0x38c83892,0x398c3981,0x392f38fc,0x39a33997,0x39913961,0x39b939ae,0x39ec39bf,0x39cf39c4,0x3a423a18,0x39e439d9,0x3a913a6a,0x39f939ef,0x3ad93ab6,
0x3a0a3a18,0x3acb3af0,0x39ec39fb,0x3a7b3aa4,0x39cf39de,0x3a223a4f,0x39b039bf,0x39c139f3,0x399139a0,0x395a398e,0x39713981,0x38eb3923,0x39503961,0x387638b1,0x392f3940,0x37f63839,
0xb921b90b,0xb816b7a4,0xb94bb936,0xb89ab859,0xb975b961,0xb917b8d9,0xb99eb98a,0xb98cb953,0xb9c6b9b2,0xb9f9b9c4,0xb9ecb9d9,0xba5dba2c,0xba12b9ff,0xbab7ba8b,0xba36ba24,0xbb07bae1,
0xba3eba53,0xbaf5bb1d,0xba12ba28,0xba9bbaca,0xb9e4b9fb,0xba36ba6a,0xb9b4b9cc,0xb9c6b9ff,0xb983b99c,0xb94bb98a,0xb950b96a,0xb8c8b90b,0xb91cb936,0xb83cb883,0xb8e6b901,0xb750b7e6,
0x38e138c0,0x379e36fc,0x39213901,0x386b381e,0x395e3940,0x38fe38b6,0x399a397c,0x39883944,0x39d339b7,0x3a0539c8,0x3a0a39ef,0x3a773a40,0x3a3e3a24,0x3adc3aab,0x3a703a57,0x3b333b09,
0x3a703a8b,0x3b1c3b47,0x3a363a53,0x3abb3aed,0x39f93a18,0x3a4a3a84,0x39b939d9,0x39ca3a0c,0x39753997,0x393d3985,0x392f3953,0x38a438f2,0x38e6390b,0x38003854,0x389a38c0,0x36a73756,
0xb70db651,0xb4aeb309,0xb83cb7c5,0xb6ebb5d1,0xb8e6b892,0xb880b7fb,0xb983b936,0xb971b8fc,0xba12b9cc,0xba42b9de,0xba91ba53,0xbaefba9d,0xbafebaca,0xbb74bb37,0xbb5abb2e,0xbbcebba6,
0xbb40bb6c,0xbbb2bbd8,0xbad9bb0f,0xbb43bb80,0xba5dba9d,0xbaa6bafa,0xb9cfba18,0xb9e0ba48,0xb92fb981,0xb8f5b96e,0xb880b8d9,0xb7d5b873,0xb788b824,0xb590b6b8,0xb5fab6c3,0xb251b460,
0x367935a2,0x34113197,0x380b374b,0x3684354f,0x38cd386e,0x386637af,0x397e3928,0x396c38ed,0x3a1e39d1,0x3a4e39e2,0x3aa93a66,0x3b043aaf,0x3b1f3ae7,0x3b8c3b4e,0x3b7d3b51,0x3be03bbd,
0x3b613b8d,0x3bc73be8,0x3af53b2e,0x3b5a3b97,0x3a703ab6,0x3ab73b0f,0x39d33a24,0x39e43a53,0x3921397c,0x38e6396a,0x385c38c0,0x37883859,0x370d37e6,0x350e3651,0x3549362e,0x30de3383,
0xb5e2b4f0,0xb2e4b023,0xb7b4b6cf,0xb61db4cc,0xb8b4b849,0xb84cb761,0xb97ab919,0xb967b8de,0xba2ab9d5,0xba59b9e6,0xbac1ba79,0xbb19bac0,0xbb3dbb03,0xbba2bb65,0xbb9cbb70,0xbbefbbd0,
0xbb7fbbaa,0xbbd8bbf4,0xbb10bb4c,0xbb6fbbac,0xba82bacd,0xbac8bb23,0xb9d7ba30,0xb9e8ba5f,0xb912b978,0xb8d7b965,0xb836b8a7,0xb73ab83e,0xb690b783,0xb48ab5e8,0xb496b596,0xaecfb244,
0x3549343b,0x31a42d58,0x37503651,0x35b33447,0x389a3824,0x38313713,0x3975390b,0x396338cf,0x3a3639d9,0x3a6539ea,0x3ad93a8b,0x3b2d3ad0,0x3b5a3b1d,0x3bb53b7a,0x3bb73b8d,0x3bf93be0,
0x3b9a3bc3,0x3be73bfc,0x3b2a3b67,0x3b833bbe,0x3a943ae4,0x3ad93b37,0x39db3a3c,0x39ec3a6a,0x39033973,0x38c83961,0x3811388d,0x36eb3824,0x3611371e,0x3405357e,0x33c034fc,0x2bc03103,
0xb061a8cf,0x25b230ac,0xb549b383,0xb32eae84,0xb816b6c3,0xb750b57e,0xb95eb8c0,0xb94bb883,0xba70b9ef,0xba9bb9ff,0xbb40bae1,0xbb83bb1d,0xbbc7bb8d,0xbbf5bbcc,0xbbffbbed,0xbbeabbff,
0xbbf2bc00,0xbbfebbe3,0xbb96bbcf,0xbbd2bbf9,0xbae9bb49,0xbb25bb8b,0xb9f1ba75,0xba01baa1,0xb8b9b95c,0xb87bb949,0xb69bb809,0xb555b734,0xb2fdb514,0xad71b2bf,0xa376af7e,0x31662966,
0x2e39a052,0xabf2b21f,0x34de3276,0x32512c5e,0x37f63673,0x3718352c,0x395a38b1,0x39473873,0x3a7b39f3,0x3aa63a03,0x3b523af0,0x3b923b2c,0x3bd63b9f,0x3bfb3bd8,0x3c003bf6,0x3bda3bfc,
0x3bfa3bff,0x3bf93bd1,0x3ba73bdd,0x3bdd3bfd,0x3af83b5b,0x3b333b99,0x39f53a80,0x3a053aab,0x38a93957,0x386b3944,0x364b37db,0x350236fc,0x31ee34a8,0x2a9331e2,0xa8062cf4,0xb2d8ad3f,
0xab5c2af8,0x2e843390,0xb472b166,0xb172a86b,0xb7bfb622,0xb6e0b4d8,0xb955b8a2,0xb942b863,0xba86b9f7,0xbab0ba08,0xbb64bb00,0xbba0bb39,0xbbe3bbaf,0xbbffbbe2,0xbbfdbbfd,0xbbc6bbf5,
0xbbffbbfa,0xbbf1bbba,0xbbb7bbe8,0xbbe7bc00,0xbb07bb6c,0xbb40bba6,0xb9f9ba8b,0xba0abab6,0xb89ab953,0xb85cb940,0xb5fab7a4,0xb4aeb6c3,0xb0deb43b,0xa484b103,0x2cf4a8cf,0x34232fc9,
0x2484ae6b,0xb086b47e,0x34053055,0x30931248,0x378835d1,0x36a73484,0x39503892,0x393d3854,0x3a9139fb,0x3abb3a0c,0x3b743b0f,0x3bad3b47,0x3bed3bbe,0x3c003beb,0x3bf63c00,0x3bae3beb,
0x3c003bf0,0x3be53ba0,0x3bc53bf2,0x3bef3c00,0x3b163b7c,0x3b4d3bb3,0x39fd3a96,0x3a0e3ac0,0x388b394e,0x384c393b,0x35a8376c,0x345a368a,0x2f97339c,0xa4203023,0xafe298b6,0xb4d8b128,
0x31c93531,0x355b37e0,0xaf652839,0x9d7f315a,0xb66db42f,0xb584b1b0,0xb939b844,0xb925b803,0xbac5ba10,0xbaecba20,0xbbb9bb53,0xbbdfbb82,0xbbffbbf2,0xbbe3bc00,0xbb91bbde,0xbaf7bb8a,
0xbbd6bb81,0xbb7cbadf,0xbbf5bbfd,0xbc00bbdd,0xbb5abbbe,0xbb88bbe3,0xba12baca,0xba22baf0,0xb83cb936,0xb7f6b923,0xb405b651,0xb15ab567,0x2a61ae84,0x31e22052,0x358a3269,0x381935a8,
0xb309b5e2,0xb5f4b841,0x2da3ac44,0xa5b2b269,0x363433b4,0x35493103,0x39343834,0x392137e6,0x3acf3a14,0x3af53a24,0x3bc43b60,0x3be73b8d,0x3bfb3bf8,0x3bd63bff,0x3b703bce,0x3ac63b6d,
0x3bc53b5f,0x3b5d3aad,0x3bfa3bf9,0x3bff3bcf,0x3b663bc9,0x3b923bea,0x3a163ad4,0x3a263afa,0x382c3931,0x37d5391e,0x335f3617,0x30ac352c,0xad582cc2,0xb2f0a89d,0xb63ab3a8,0xb869b63f,
0x34233690,0x368a3890,0xabc02e6b,0x2a613377,0xb5fab309,0xb50eb055,0xb92fb824,0xb91cb7c5,0xbad9ba18,0xbafeba28,0xbbcebb6c,0xbbedbb97,0xbbf6bbfc,0xbbc7bbfd,0xbb4cbbba,0xba93bb4d,
0xbbafbb38,0xbb3cba77,0xbbfebbf2,0xbbfcbbbf,0xbb72bbd3,0xbb9cbbf0,0xba1abadd,0xba2abb03,0xb81cb92d,0xb7b4b919,0xb2b3b5dc,0xaffbb4f0,0x2f7ea9fd,0x33fd2c12,0x36e53472,0x38b636d4,
0xb4c0b73a,0xb71eb8dc,0x2839b048,0xacf4b441,0x35bf325d,0x34d22f4c,0x392a3813,0x391737a4,0x3ae23a1c,0x3b073a2c,0x3bd73b77,0x3bf33ba1,0x3bee3bff,0x3bb63bfa,0x3b233ba4,0x3a5b3b2a,
0x3b973b0d,0x3b183a3e,0x3c003be9,0x3bf73bad,0x3b7d3bdb,0x3ba63bf5,0x3a1e3ae7,0x3a2e3b0c,0x380b3928,0x37933914,0x320735a2,0x2e9d34b4,0xb0d124e9,0xb484add5,0xb78eb50e,0xb901b767,
0xb97239ba,0x39dc3996,0xb8323ab5,0x3ad0385d,0x3927b9fe,0xba1fb94d,0x37b7bae9,0xbb02b807,0xb8d83a3f,0x3a5e3900,0xb7053b1a,0x3b30375e,0x3887ba7c,0xba99b8b0,0x364ebb46,0xbb5ab6aa,
0xb90039dc,0x3a3f3972,0xad7e3be6,0x3bf83115,0x3807ba99,0xbae9b887,0xabd9bc00,0xbbfca248,0xb5f13b30,0x3b6e3705,0x32a13bed,0x3bd4b04e,0x3365bba0,0xbbc9b4d5,0xb593bbaf,0xbb803475,
0xb88739fe,0x3a99394d,0x35f13bbc,0x3b6eb414,0x3593bb1a,0xbb80b75e,0xb8b0bb02,0xba7c37b7,0xaf0e3bc9,0x3bf43365,0x3a1f39dc,0x3927b972,0xb04ebc00,0xbbed2248,0xbb30b85d,0xb7053ab5,
0xb8073a1f,0x3ae93927,0x39fe3a3f,0x394db900,0x31dbbb80,0xbbddb593,0xbb6eb832,0xb5f13ad0,0x31153c00,0x3be62248,0x3bff32a1,0x28b6bbd4,0xb7b7bb91,0xbb023534,0xbba0304e,0x34d53bed,
0xb7053a3f,0x3b303900,0x3bbc375e,0x3414bb1a,0x2248bbc9,0xbc00b365,0xbbdda8b6,0x31db3bff,0x36aa3bd4,0x3b46b2a1,0x3a7cb64e,0xb8b0bb5a,0xba1fba5e,0xb92738d8,0xb7b739fe,0x3b02394d,
0xb5f13a5e,0x3b6e38d8,0x3bd42bd9,0xb2a1bbfc,0xb115bbf4,0xbbe6af0e,0xb9dc375e,0x39723b1a,0x39273b46,0x3a1fb6aa,0x3475bad0,0xbbafb832,0xbb91b887,0xb5343a99,0x34143c00,0x3bbc2248,
0xb4d53a7c,0x3ba038b0,0x3a3fb593,0xb900bb80,0xb534bc00,0xbb912248,0xb4143ab5,0x3bbc385d,0x3a993a5e,0x3887b8d8,0xb5f1bbfc,0xbb6e2bd9,0xbbffb475,0x28b63baf,0x3ad03a1f,0x3832b927,
0xb3653a99,0x3bc93887,0x36aab996,0xbb46b9ba,0xb7b7bbed,0xbb02304e,0x34d53bfc,0x3ba02bd9,0x3b913927,0x3534ba1f,0xbae9ba3f,0xb8073900,0xbb5a28b6,0x364e3bff,0x3bd43115,0xb2a1bbe6,
0xb1153ab5,0x3be6385d,0xa8b6bb6e,0xbbffb5f1,0xb900bbbc,0xba3f3414,0x3a1f3b30,0x3927b705,0x3bfc375e,0x2bd9bb1a,0xbbedb475,0x304e3baf,0xb9ba3593,0x39963b80,0x3887b832,0xba99bad0,
0xad7e3ad0,0x3bf83832,0xb7b7bbff,0xbb0228b6,0xb9febb6e,0xb94d35f1,0x3bed3887,0x304eba99,0x3bd43414,0xb2a1bbbc,0xb9963534,0x39ba3b91,0xb6aa3900,0x3b463a3f,0xb115bba0,0xbbe6b4d5,
0xa2483ae9,0x3c003807,0xba99bb30,0xb8873705,0xbad0bb02,0xb83237b7,0x3b462d7e,0xb6aabbf8,0x3b1a28b6,0xb75ebbff,0xaf0e3a7c,0x3bf438b0,0xabd93ab5,0x3bfc385d,0xba5ebb5a,0xb8d8364e,
0x2bd93b02,0x3bfc37b7,0xbbedb927,0xb04e3a1f,0xbb6eba7c,0xb5f138b0,0x385db6aa,0xbab5bb46,0x39dcb1db,0xb972bbdd,0x38323c00,0x3ad02248,0x34d53bbc,0x3ba03414,0xbbf4b705,0x2f0e3b30,
0x304e3b1a,0x3bed375e,0xbb91b475,0x35343baf,0xbbd4b9dc,0xb2a13972,0x2248ba7c,0xbc00b8b0,0x3832b64e,0xbad0bb5a,0x3b803a99,0x3593b887,0x39003bfc,0x3a3fabd9,0xb9273414,0x3a1f3bbc,
0x32a13b30,0x3bd43705,0xb996304e,0x39ba3bed,0xbbffb927,0xa8b63a1f,0xb832bbf4,0xbad0af0e,0x3475b8b0,0xbbafba7c,0x3ba03593,0xb4d5bb80,0x3ae93b6e,0x3807b5f1,0x2bd93a99,0x3bfc3887,
0x34753b46,0x3baf36aa,0xb4d53832,0x3ba03ad0,0xbbedb85d,0x304e3ab5,0xbb30bb5a,0xb705364e,0x2248b9fe,0xbc00b94d,0x3887b414,0xba99bbbc,0x3be63a1f,0x3115b927,0x39dc3bf4,0x3972af0e,
0x35933b5a,0x3b80364e,0x31153a99,0x3be63887,0xbba0b705,0x34d53b30,0xbbf4b8d8,0x2f0e3a5e,0xb414bb02,0xbbbcb7b7,0xabd9ba1f,0xbbfcb927,0x3bd43832,0xb2a1bad0,0x3c003972,0xa248b9dc,
0x36aa3b6e,0x3b4635f1,0x38b03bdd,0x3a7c31db,0xbb1ab534,0x375e3b91,0xba3fb04e,0x39003bed,0xb807bbaf,0xbae9b475,0xb94dbbf8,0xb9fead7e,0x3ab53365,0xb85dbbc9,0x39ba28b6,0xb996bbff,
0x37b73b80,0x3b023593,0x3b1a3bc9,0x375eb365,0xba5eb2a1,0x38d83bd4,0xb53435f1,0x3b913b6e,0xb9babbfc,0xb996abd9,0xbbddbae9,0xb1db3807,0x38b0ad7e,0xba7cbbf8,0x28b6b900,0xbbffba3f,
0x385d3b91,0x3ab53534,0x3c003a5e,0x2248b8d8,0xb972ad7e,0x39dc3bf8,0x33653a3f,0x3bc93900,0xbb02bbe6,0xb7b73115,0xbb1ab6aa,0x375e3b46,0x3414b64e,0xbbbcbb5a,0xb94dbbdd,0xb9feb1db,
0x38d83ba0,0x3a5e34d5,0x3b3037b7,0xb705bb02,0xb85d28b6,0x3ab53bff,0x39ba3be6,0x39963115,0xbbc9bb6e,0xb36535f1,0xb6aa31db,0x3b463bdd,0xaf0eb94d,0xbbf4b9fe,0xbbf8bae9,0xad7e3807,
0x394d3baf,0x39fe3475,0x38d82d7e,0xba5ebbf8,0xb64e3115,0x3b5a3be6,0x3bd43b80,0x32a1b593,0xbbffba99,0x28b63887,0x336539ba,0x3bc93996,0xb75ebae9,0xbb1ab807,0xba3fb534,0x39003b91,
0x39ba3bbc,0x39963414,0x31dbb534,0xbbddbb91,0xb3653475,0x3bc93baf,0x3b803927,0xb593ba1f,0xbba0b972,0x34d539dc,0x3a3f3be6,0x39003115,0xb9febbd4,0xb94db2a1,0xb04e35f1,0x3bed3b6e,
0x3a1f3bc9,0x39273365,0xb475b972,0xbbafb9dc,0xabd9364e,0x3bfc3b5a,0x38d831db,0xba5ebbdd,0xbab5b807,0x385d3ae9,0x3c003b30,0x2248b705,0xbb80bbf4,0xb5932f0e,0x38b03b1a,0x3a7c375e,
0x3a7c3bd4,0x38b032a1,0xb972bb5a,0xb9dcb64e,0x2f0e3807,0x3bf43ae9,0x2d7eb534,0xbbf8bb91,0xb94db4d5,0x39fe3ba0,0x3a5e37b7,0xb8d8bb02,0xbc00bb46,0x224836aa,0x3bdd3bc9,0x31dbb365,
0x3ad03bdd,0x383231db,0xbb80bc00,0xb5932248,0x347538d8,0x3baf3a5e,0xb75eb9fe,0xbb1ab94d,0xb705ad7e,0x3b303bf8,0x3414af0e,0xbbbcbbf4,0xbb6eb9dc,0x35f13972,0x3ab538b0,0xb85dba7c,
0x3b1a3be6,0x375e3115,0xbbf4bb46,0x2f0e36aa,0x37053996,0x3b3039ba,0xbae9bbd4,0xb807b2a1,0xb1db304e,0x3bdd3bed,0xb64eb94d,0xbb5ab9fe,0xb9dcb7b7,0x39723b02,0x3365ad7e,0xbbc9bbf8,
0x3b5a3bed,0x364e304e,0xbab5b94d,0x385d39fe,0x38b03a3f,0x3a7c3900,0xbbffbba0,0x28b634d5,0x2d7e3593,0x3bf83b80,0xbb02bbc9,0xb7b7b365,0xb705b1db,0x3b303bdd,0xb807b9ba,0xbae9b996,
0x3b913bf4,0x35342f0e,0xb807b4d5,0x3ae93ba0,0x39ba3ad0,0x39963832,0xba99b972,0x388739dc,0x3593385d,0x3b803ab5,0xbbe6bb6e,0x311535f1,0xad7e304e,0x3bf83bed,0xbbafbbfc,0xb475abd9,
0x3bbc3bf8,0x34142d7e,0xabd92f0e,0x3bfc3bf4,0x3a993b46,0x388736aa,0xb64eb365,0x3b5a3bc9,0x38b039ba,0x3a7c3996,0xb972b85d,0x39dc3ab5,0x34753705,0x3baf3b30,0xbb1aba5e,0x375e38d8,
0x3bdd3bfc,0x31db2bd9,0x364e3807,0x3b5a3ae9,0x3b463ba0,0x36aa34d5,0x31153475,0x3be63baf,0x3a3f3ad0,0x39003832,0xad7e28b6,0x3bf83bff,0x38d83996,0x3a5e39ba,0xb534b2a1,0x3b913bd4,
0x3bf43bff,0x2f0e28b6,0x3a1f3a7c,0x392738b0,0x3bbc3bdd,0x341431db,0x394d39ba,0x39fe3996,0x3b5a3b91,0x364e3534,0x385d38d8,0x3ab53a5e,0x3ad03b1a,0x3832375e,0x36aa37b7,0x3b463b02,
0x3bff3c00,0x28b62248,0x3bc93bd4,0x336532a1,0x3bf83bfc,0x2d7e2bd9,0x3baf3bbc,0x34753414,0x3bed3bf4,0x304e2f0e,0x3b913ba0,0x353434d5,0x3bdd3be6,0x31db3115,0x3b6e3b80,0x35f13593,
0xb5933b6e,0x3b8035f1,0xb1153bdd,0x3be631db,0x34d5bb91,0xbba0b534,0x2f0ebbed,0xbbf4b04e,0xb4143baf,0x3bbc3475,0xabd93bf8,0x3bfc2d7e,0x32a1bbc9,0xbbd4b365,0x2248bbff,0xbc00a8b6,
0x37b73b46,0x3b02b6aa,0x3b1a3832,0x375ebad0,0xb8d8bab5,0xba5e385d,0xbb91b64e,0xb5343b5a,0x39ba39fe,0x3996b94d,0x3bdd3414,0x31dbbbbc,0xba7cb927,0xb8b03a1f,0xbbffaf0e,0xa8b63bf4,
0x3bd43534,0x32a1bb91,0x39bab8d8,0xb996ba5e,0xbbffad7e,0x28b63bf8,0xb8323a3f,0x3ad03900,0x3bafb115,0xb475bbe6,0x34d5bb46,0xbba0b6aa,0xbae9364e,0x38073b5a,0xabd93bdd,0x3bfc31db,
0x3a5eb75e,0xb8d8bb1a,0xb705bbaf,0xbb303475,0xb85d39dc,0x3ab53972,0x39ba3a7c,0x3996b8b0,0x3365bb5a,0xbbc9b64e,0xbb46b887,0xb6aa3a99,0x2f0e3bfc,0x3bf42bd9,0x3bf83414,0x2d7ebbbc,
0x2bd9bbaf,0xbbfcb475,0xbbedad7e,0x304e3bf8,0x35f13be6,0x3b6eb115,0x3ab5b593,0xb85dbb80,0xb9dcba99,0xb9723887,0xb83239ba,0x3ad03996,0x3ba03807,0x34d5bae9,0x2f0ebb91,0xbbf4b534,
0xb9babae9,0xb9963807,0xb1db3b30,0x3bdd3705,0x3bc937b7,0x3365bb02,0xb593bbf8,0xbb802d7e,0xbba028b6,0x34d53bff,0x3a3f3a7c,0x3900b8b0,0x394db85d,0xb9febab5,0xbbedb64e,0xb04e3b5a,
0xbbf8b365,0x2d7e3bc9,0x3b0239dc,0x37b7b972,0x39feb64e,0xb94dbb5a,0xbbedb1db,0x304e3bdd,0xb2a13ae9,0x3bd43807,0x39bab705,0xb996bb30,0xb6aabbf4,0xbb462f0e,0xb1153b1a,0x3be6375e,
0xb8b0385d,0x3a7c3ab5,0x39dcb5f1,0xb972bb6e,0xaf0ebbbc,0xbbf4b414,0xad7e3b30,0x3bf83705,0x39fe3b1a,0x394db75e,0xb8d8bbaf,0xba5e3475,0xbc00b593,0x22483b80,0x3bdd3832,0x31dbbad0,
0x33653bdd,0x3bc931db,0xb6aabc00,0xbb462248,0xbb02ba5e,0xb7b738d8,0x3ba0394d,0x34d5b9fe,0x3b912d7e,0xb534bbf8,0xbae92f0e,0x38073bf4,0xb64e3972,0x3b5a39dc,0x32a1ba7c,0xbbd4b8b0,
0x3b1a3a7c,0x375eb8b0,0xbbf4b593,0x2f0e3b80,0xbb30a248,0x37053c00,0x3807b85d,0xbae9bab5,0x31dbba5e,0xbbddb8d8,0x364e3bfc,0x3b5a2bd9,0x39723baf,0x39dcb475,0xbbc9b927,0xb3653a1f,
0x3b6e304e,0xb5f1bbed,0xb2a139fe,0x3bd4394d,0xb1153a3f,0x3be63900,0xb9dcbba0,0xb97234d5,0xba1fbb80,0xb9273593,0x3baf3365,0xb475bbc9,0x3b9131db,0xb534bbdd,0xb41439ba,0x3bbc3996,
0x3534b900,0xbb91ba3f,0x3ae93b1a,0x3807b75e,0x39ba3bc9,0x3996b365,0xba9928b6,0x38873bff,0xbb80b2a1,0x35933bd4,0xb115bb5a,0xbbe6b64e,0x2d7eba5e,0xbbf8b8d8,0x3baf39fe,0x3475b94d,
0xb807bbf8,0xbae9ad7e,0x39feaf0e,0xb94dbbf4,0x3bdd36aa,0xb1dbbb46,0x35f13bc9,0x3b6e3365,0xb11539ba,0x3be63996,0xbbffb85d,0x28b63ab5,0xbb02bb30,0xb7b73705,0x34d5b8d8,0xbba0ba5e,
0xbbddb9fe,0xb1db394d,0xb64ebbbc,0xbb5ab414,0x36aab75e,0xbb46bb1a,0x3be637b7,0xb115bb02,0x3a3f3bc9,0x3900b365,0xad7e39dc,0x3bf83972,0xba5ea248,0x38d83c00,0xbb91bab5,0xb534385d,
0xba3fa8b6,0x39003bff,0xbbf8b8b0,0x2d7e3a7c,0xb807bbdd,0xbae9b1db,0x2bd9b9ba,0xbbfcb996,0x3b6e3534,0xb5f1bb91,0x3bd43a5e,0x32a1b8d8,0x33653b1a,0x3bc9375e,0xb59337b7,0x3b803b02,
0xa8b63996,0x3bff39ba,0xb365385d,0x3bc93ab5,0xbbf8b9fe,0xad7e394d,0xbbafbae9,0xb4753807,0x304eb900,0xbbedba3f,0x3534b75e,0xbb91bb1a,0x3bdd3a7c,0x31dbb8b0,0x3b6e3b46,0x35f1b6aa,
0x39dc3c00,0x3972a248,0x3ad03bd4,0x3832b2a1,0xb9272bd9,0x3a1f3bfc,0xb7b73414,0x3b023bbc,0xba5ebbf4,0xb8d82f0e,0xbb30bba0,0xb70534d5,0x3887b115,0xba99bbe6,0x364eb593,0xbb5abb80,
0x3bf43972,0xaf0eb9dc,0x3a1f3115,0xb927bbe6,0x34143a99,0x3bbc3887,0x39fe3c00,0x394d2248,0xbb5ab705,0x364e3b30,0xb85d304e,0x3ab53bed,0xb832bba0,0xbad0b4d5,0xbb46bbaf,0xb6aa3475,
0x3887abd9,0xba99bbfc,0xb5f1bae9,0xbb6eb807,0x3b803ba0,0x3593b4d5,0x3a7c3475,0xb8b0bbaf,0xaf0e3832,0x3bf43ad0,0x3a1f3bff,0x392728b6,0xbbedb996,0x304e39ba,0xb70532a1,0x3b303bd4,
0xb414ba1f,0xbbbcb927,0xbbfcba3f,0x2bd93900,0x3a993593,0xb887bb80,0xb64ebad0,0xbb5ab832,0x3a7c3c00,0x38b02248,0x39dc32a1,0xb972bbd4,0xb4753534,0x3baf3b91,0x3b1a3bed,0x375eb04e,
0xbb30bbf4,0xb7052f0e,0xb41434d5,0x3bbc3ba0,0x2248b832,0xbc00bad0,0xbbddb9dc,0x31db3972,0x3b46385d,0xb6aabab5,0xb8b0bb6e,0xba7cb5f1,0x3a1f3bed,0x3927304e,0x37b7abd9,0xbb02bbfc,
0xbb5ab8d8,0x364e3a5e,0x3ab53bfc,0x385d2bd9,0xba7cbbf4,0xb8b0af0e,0xa8b6375e,0x3bff3b1a,0x2d7eb6aa,0xbbf8bb46,0xbb02b832,0x37b73ad0,0x3b303887,0xb705ba99,0xbae9bc00,0xb807a248,
0xb4d53115,0x3ba03be6,0x3a3f36aa,0xb900bb46,0xbb91b996,0x353439ba,0x3bbc3bd4,0x3414b2a1,0xba99bbed,0xb887b04e,0x35f139fe,0x3b6e394d,0xa8b6b7b7,0xbbffbb02,0xb832ad7e,0x3ad03bf8,
0x38323a99,0x3ad03887,0xb593b996,0xbb80b9ba,0xb475304e,0x3baf3bed,0x375e2bd9,0xbb1abbfc,0xbb30b927,0x37053a1f,0x3bbc3a3f,0xb414b900,0xbb6ebbff,0xb5f128b6,0x3ab53be6,0x385d3115,
0x3be63bd4,0x3115b2a1,0xbbffbb5a,0x28b6364e,0x39003ae9,0x3a3f3807,0xba1fbb91,0xb927b534,0xabd934d5,0x3bfc3ba0,0xb04eb7b7,0xbbedbb02,0xb9bab6aa,0x39963b46,0x38873365,0xba99bbc9,
0x3a1f3832,0xb927bad0,0xb47528b6,0x3baf3bff,0x3bfc3b6e,0xabd9b5f1,0xba5eb887,0x38d83a99,0x3ab53bbc,0x385d3414,0xbc00bb91,0x22483534,0x35933900,0x3b803a3f,0xba7cbba0,0xb8b0b4d5,
0x2248b414,0xbc00bbbc,0x3a993b91,0x38873534,0x38323475,0xbad0bbaf,0x36aa3927,0x3b463a1f,0x3b1a39dc,0xb75eb972,0xaf0e3115,0x3bf43be6,0x3bfc3bd4,0x2bd9b2a1,0xb8d8b5f1,0x3a5e3b6e,
0xb9febb02,0xb94db7b7,0x3a5e3927,0xb8d8ba1f,0xb64eb8b0,0xbb5aba7c,0x3bd43b46,0xb2a1b6aa,0x28b6b1db,0xbbffbbdd,0x3bc93c00,0x33652248,0x375e3414,0xbb1abbbc,0x3a3f3b30,0x39003705,
0xbbedbba0,0x304e34d5,0xb534b7b7,0xbb91bb02,0xbbd4bbff,0xb2a1a8b6,0x2248b115,0xbc00bbe6,0xbad0bb6e,0xb832b5f1,0x359331db,0xbb80bbdd,0xb900b9fe,0xba3fb94d,0x39273807,0xba1fbae9,
0xb85db705,0x3ab53b30,0xbc00bbed,0x2248304e,0xb9dcb927,0x39723a1f,0xbbc9bbf4,0xb365af0e,0xbb02ba7c,0x37b738b0,0xbb1abb80,0xb75eb593,0xbbbcbb6e,0x341435f1,0xb9feba99,0xb94db887,
0x34753593,0x3baf3b80,0xb4d5b365,0x3ba03bc9,0x304e32a1,0x3bed3bd4,0xb705b5f1,0x3b303b6e,0xa2482bd9,0x3c003bfc,0xb887b807,0x3a993ae9,0xb115ad7e,0x3be63bf8,0xb972b900,0x39dc3a3f,
0x3b463b5a,0x36aa364e,0x3a7c3a99,0x38b03887,0x3b1a3b30,0x375e3705,0x3a3f3a5e,0x390038d8,0x3ae93b02,0x380737b7,0x39fe3a1f,0x394d3927,0x3ab53ad0,0x385d3832,0x39ba39dc,0x39963972,
0x28b63c00,0x3bffa248,0x33653bd4,0x3bc9b2a1,0xad7ebbfc,0xbbf82bd9,0xb475bbbc,0xbbaf3414,0x304e3bf4,0x3bedaf0e,0x35343ba0,0x3b91b4d5,0xb1dbbbe6,0xbbdd3115,0xb5f1bb80,0xbb6e3593,
0x3bf4a8b6,0xaf0ebbff,0x3a1fb8b0,0xb927ba7c,0xbbbc31db,0x34143bdd,0xb94d3996,0x39fe39ba,0x3b5ab534,0xb64ebb91,0x385dba5e,0xbab5b8d8,0xbad0375e,0x38323b1a,0xb6aa3b02,0x3b4637b7,
0xb1dbbbfc,0xbbdd2bd9,0xbb5ab807,0xb64e3ae9,0x36aa3ba0,0x3b46b4d5,0x3be63475,0x3115bbaf,0xb900bad0,0xba3f3832,0xbbf8a8b6,0x2d7e3bff,0x3a5e3996,0x38d8b9ba,0x3b91b2a1,0xb534bbd4,
0xbbbc2d7e,0x34143bf8,0x2bd93bf4,0x3bfc2f0e,0x3a99b6aa,0xb887bb46,0xb64ebbc9,0xbb5a3365,0xb8b03996,0x3a7c39ba,0x39723ab5,0x39dcb85d,0x3475bb30,0xbbafb705,0xbb1ab8d8,0xb75e3a5e,
0x35343bf4,0x3b91af0e,0x3ae9b4d5,0xb807bba0,0xb996bad0,0xb9ba3832,0xb8873972,0x3a9939dc,0x3b80385d,0x3593bab5,0x3115bb6e,0xbbe6b5f1,0xbbf8b04e,0x2d7e3bed,0x34753bfc,0x3bafabd9,
0x3b5ab04e,0xb64ebbed,0xbab5b9fe,0xb85d394d,0xb8b03900,0x3a7c3a3f,0x3bff34d5,0x28b6bba0,0x2d7ebb80,0xbbf8b593,0xbb023365,0x37b73bc9,0x37053bdd,0x3b30b1db,0x3807b996,0xbae9b9ba,
0xb75ebbe6,0xbb1a3115,0xaf0e3b46,0x3bf436aa,0x3b303996,0x3705b9ba,0xb807bbd4,0xbae932a1,0xbbddb04e,0x31db3bed,0x3b5a394d,0x364eb9fe,0x3972b7b7,0xb9dcbb02,0xbbc9ad7e,0x33653bf8,
0xbad031db,0x38323bdd,0x3b802248,0xb593bc00,0x3475ba5e,0xbbafb8d8,0xb75e394d,0x3b1a39fe,0x37053bf8,0x3b30ad7e,0xb414bbf4,0xbbbcaf0e,0xbb6eb972,0xb5f139dc,0x3ab53a7c,0x385db8b0,
0x38b03bd4,0x3a7cb2a1,0xb9dcbb5a,0xb972364e,0xbbf4b807,0xaf0e3ae9,0x3bf83534,0xad7ebb91,0x39feb4d5,0xb94dbba0,0xb8d837b7,0x3a5e3b02,0xa2483b46,0x3c0036aa,0xb1dbbbc9,0xbbddb365,
0x3a1fb365,0xb927bbc9,0xb47539dc,0x3baf3972,0x2bd93b5a,0x3bfc364e,0xb8d8bbdd,0xba5e31db,0xbab5bae9,0xb85d3807,0x3c003705,0xa248bb30,0x3b802f0e,0xb593bbf4,0xb8b0375e,0x3a7c3b1a,
0xb996bbbc,0xb9ba3414,0x3bdd3534,0xb1dbbb91,0x3bc93475,0xb365bbaf,0xb5933927,0x3b803a1f,0xb4d53972,0x3ba039dc,0xb900bbe6,0xba3f3115,0xb94dbbd4,0xb9fe32a1,0x3bed35f1,0xb04ebb6e,
0xb94d3475,0x39fe3baf,0xb8d8bbf8,0xba5e2d7e,0xb64ebbe6,0xbb5ab115,0x3bd43593,0xb2a1bb80,0x3bff3887,0x28b6ba99,0xb3653996,0x3bc939ba,0xb75e3807,0x3b1a3ae9,0xba3fbb91,0xb9003534,
0x3a5e3ba0,0x38d8b4d5,0xb70537b7,0x3b303b02,0xbab5a8b6,0x385d3bff,0xb996bbe6,0xb9ba3115,0xb365bb6e,0xbbc9b5f1,0x3b4631db,0xb6aabbdd,0x3bf4394d,0x2f0eb9fe,0x2d7e3ae9,0x3bf83807,
0x385db534,0xbab5bb91,0x3c0038d8,0xa248ba5e,0x39723bf8,0x39dcad7e,0xb3653900,0x3bc93a3f,0xbb02b115,0x37b73be6,0xbb1abb46,0xb75e36aa,0xb414bb5a,0xbbbcb64e,0x394db1db,0xb9febbdd,
0xbb02bb80,0xb7b73593,0xb75ebbc9,0xbb1ab365,0x38d8b2a1,0xba5ebbd4,0x3b9135f1,0xb534bb6e,0x39963bfc,0x39baabd9,0x31db3ae9,0x3bdd3807,0xba7cad7e,0x38b03bf8,0xbbffb900,0x28b63a3f,
0xb6aa35f1,0x3b463b6e,0xb8b031db,0x3a7c3bdd,0xbb1abb91,0xb75e3534,0xba3fbbed,0xb900304e,0x3807b475,0xbae9bbaf,0x394dad7e,0xb9febbf8,0x3ab53bc9,0x385db365,0x39ba3bff,0x3996a8b6,
0x3b803b5a,0x3593b64e,0x3be63a99,0x3115b887,0xb4d53705,0x3ba03b30,0xaf0e38d8,0x3bf43a5e,0xbbbcbb02,0xb41437b7,0xbbfcba1f,0xabd93927,0x32a1b832,0xbbd4bad0,0x2248b972,0xbc00b9dc,
0x3475b6aa,0xbbafbb46,0xb4d5bad0,0xbba0b832,0x3bed3ab5,0x304eb85d,0x3b30364e,0xb705bb5a,0x2248394d,0x3c0039fe,0x38873bbc,0x3a993414,0xbbe6b927,0x31153a1f,0xb9dcaf0e,0x39723bf4,
0xbbd4bb30,0xb2a13705,0xb9bab04e,0x39963bed,0xa8b6b927,0xbbffba1f,0xbad0bbf4,0xb8322f0e,0x3baf38b0,0xb475ba7c,0x34d5b593,0xbba0bb80,0x38073b6e,0x3ae935f1,0x3bfc3a99,0x2bd9b887,
0xb04e375e,0x3bed3b1a,0x3b913baf,0x3534b475,0xbbd4b972,0x32a139dc,0x224838b0,0x3c003a7c,0xb832bb5a,0xbad0b64e,0xbb80b887,0x35933a99,0x39002bd9,0xba3fbbfc,0xb927bbbc,0xba1fb414,
0x3bfc3b02,0x2bd9b7b7,0xb04eb927,0xbbedba1f,0x35f13a7c,0x3b6e38b0,0x3ab536aa,0xb85dbb46,0xb972b1db,0x39dc3bdd,0x3ad03c00,0x3832a248,0xbba0bbbc,0xb4d53414,0xaf0e3705,0x3bf43b30,
0xa248b807,0xbc00bae9,0xba99b705,0x38873b30,0x3ad037b7,0xb832bb02,0xbb46bbf8,0xb6aa2d7e,0x3b1a3bff,0x375ea8b6,0xaf0eb8b0,0xbbf4ba7c,0x2bd9385d,0x3bfc3ab5,0x3a5e364e,0xb8d8bb5a,
0xbbf8bad0,0x2d7e3832,0x3b023bff,0x37b728b6,0xb94dbb6e,0xb9feb5f1,0x304e3887,0x3bed3a99,0x32a1b414,0xbbd4bbbc,0xb9bab534,0x39963b91,0x3b463900,0xb6aaba3f,0xbbe6bba0,0xb11534d5,
0x3115385d,0x3be63ab5,0x28b6b5f1,0xbbffbb6e,0xb900b414,0x3a3f3bbc,0x3a1f3705,0xb927bb30,0xbbfcbb1a,0x2bd9375e,0x3bed3baf,0x304eb475,0xb9babb80,0xb996b593,0x38873ad0,0x3a993832,
0x3bc93a99,0xb365b887,0xbb46b996,0x36aa39ba,0x3b023bed,0x37b7304e,0xbba0bbfc,0xb4d52bd9,0x35343927,0x3b913a1f,0xb807ba3f,0xbae9b900,0xb64ea8b6,0x3b5a3bff,0x32a1b115,0xbbd4bbe6,
0xb4d5b8b0,0xbba0ba7c,0x3a3f3b80,0x39003593,0x35342248,0xbb91bc00,0x3414385d,0x3bbc3ab5,0x3a9938d8,0xb887ba5e,0xb5f1abd9,0x3b6e3bfc,0x3bff3baf,0x28b6b475,0xbad0b927,0x38323a1f,
0xbb6eba5e,0x35f138d8,0x32a1abd9,0xbbd4bbfc,0xbbe6bbf4,0xb1152f0e,0x3972375e,0xb9dcbb1a,0xba1fbb46,0xb927b6aa,0x3baf3ad0,0xb475b832,0xb534b887,0xbb91ba99,0x3bbc3c00,0x3414a248,
0x37053900,0x3b303a3f,0xbbbcbb1a,0x3414375e,0x22483365,0x3c003bc9,0xbbddbbff,0xb1db28b6,0xb6aab2a1,0x3b463bd4,0xba7cbb5a,0xb8b0b64e,0xba1fb8d8,0x39273a5e,0xb7b7b94d,0xbb02b9fe,
0x3ae93a1f,0xb807b927,0x394d3a3f,0x39fe3900,0x3bdd3b80,0xb1dbb593,0x35f13832,0x3b6e3ad0,0x3be63c00,0x3115a248,0x28b632a1,0x3bff3bd4,0x3b023b91,0x37b73534,0xb4d5b04e,0x3ba03bed,
0xb887b94d,0xba99b9fe,0x35f13414,0xbb6ebbbc,0xb593b75e,0xbb80bb1a,0x38b037b7,0xba7cbb02,0xaf0eb365,0xbbf4bbc9,0x3a1f3972,0xb927b9dc,0x304e2248,0xbbedbc00,0x3b303ab5,0xb705b85d,
0xba3fb9dc,0x39003972,0xbbf8bbe6,0x2d7e3115,0xbae9ba99,0x38073887,0xbbfcbc00,0xabd92248,0xbb6ebb30,0x35f13705,0xbbd4bbed,0xb2a1b04e,0xbbc9bba0,0x336534d5,0xbb80bbaf,0xb593b475,
0x39723996,0x39dc39ba,0x3832385d,0x3ad03ab5,0x3927394d,0x3a1f39fe,0x37b73807,0x3b023ae9,0x38d83900,0x3a5e3a3f,0x3705375e,0x3b303b1a,0x388738b0,0x3a993a7c,0x364e36aa,0x3b5a3b46,
0x36aa3b5a,0x3b46b64e,0x38b03a99,0x3a7cb887,0xb75ebb30,0xbb1a3705,0xb900ba5e,0xba3f38d8,0x38073b02,0x3ae9b7b7,0x394d3a1f,0x39feb927,0xb85dbad0,0xbab53832,0xb996b9dc,0xb9ba3972,
0x3475bb80,0xbbafb593,0xb4d5bbc9,0xbba03365,0xb04e3bd4,0x3bed32a1,0x37053b6e,0x3b30b5f1,0xa248bbfc,0xbc00abd9,0xb887bae9,0xba993807,0x31153bf8,0x3be6ad7e,0x39723a3f,0x39dcb900,
0xbab53705,0x385d3b30,0xa2483bed,0x3c00304e,0x3972b927,0xb9dcba1f,0xb365bbf4,0xbbc92f0e,0xb7b73a7c,0x3b0238b0,0x375e3b80,0x3b1ab593,0x3414bb6e,0xbbbcb5f1,0xb94dba99,0xb9fe3887,
0x3bed34d5,0x304ebba0,0x3534bb02,0xbb91b7b7,0xbbd428b6,0x32a13bff,0x22483be6,0x3c003115,0x3ad0b5f1,0xb832bb6e,0xb593bbdd,0xbb8031db,0xb900394d,0x3a3f39fe,0x39273ae9,0x3a1fb807,
0xb94dbb02,0xb9fe37b7,0xb8d83927,0x3a5e3a1f,0x3b5a38b0,0x364eba7c,0x32a1bb46,0xbbd4b6aa,0xbbffb1db,0x28b63bdd,0x33653c00,0x3bc9a248,0x3b1ab414,0xb75ebbbc,0xb900bb30,0xba3f3705,
0x22483bbc,0x3c003414,0x3a99b534,0xb887bb91,0xb832bbaf,0xbad03475,0xb6aa3a1f,0x3b463927,0x3b1a3972,0x375eb9dc,0xaf0ebbe6,0xbbf4b115,0xbbfcb2a1,0x2bd93bd4,0x38d83b6e,0x3a5eb5f1,
0x3927b832,0xba1fbad0,0xbbafa8b6,0x34753bff,0xabd93b6e,0x3bfc35f1,0x38d8b887,0xba5eba99,0xb85dbbbc,0xbab53414,0xa2483b91,0x3c003534,0x3b803900,0x3593ba3f,0xb8b0bba0,0xba7c34d5,
0xbbe6b2a1,0x31153bd4,0x3bff364e,0x28b6bb5a,0x3900b807,0xba3fbae9,0xba1f3534,0x39273b91,0x2bd93ba0,0x3bfc34d5,0x304ebb02,0xbbedb7b7,0xb9babb46,0xb99636aa,0x38873bc9,0x3a99b365,
0x3ad03a99,0x3832b887,0xbb80b996,0xb59339ba,0xbbafb04e,0x34753bed,0x3b1aabd9,0xb75ebbfc,0x3705b927,0xbb30ba1f,0xb4143a3f,0x3bbc3900,0x35f13bff,0x3b6e28b6,0xb85dbbe6,0xbab53115,
0xb4d5bbe6,0xbba0b115,0x3a3f3b46,0x3900b6aa,0x3b9139ba,0x3534b996,0xbbbcb2a1,0x34143bd4,0xba99304e,0x38873bed,0x35f1b94d,0xbb6eb9fe,0x28b6bb02,0xbbffb7b7,0x38323bf8,0x3ad0ad7e,
0xb64e38d8,0x3b5a3a5e,0xb85dbbfc,0xbab52bd9,0xb8b0bbf4,0xba7c2f0e,0x3bff375e,0xa8b6bb1a,0x3bf836aa,0xad7ebb46,0xb7b73832,0x3b023ad0,0xb7053887,0x3b303a99,0xb807bc00,0xbae92248,
0x3b302f0e,0xb705bbf4,0x34143ba0,0x3bbc34d5,0x22483ad0,0x3c003832,0xbbddb972,0xb1db39dc,0xbb46bab5,0xb6aa385d,0x38b0b5f1,0xba7cbb6e,0x3a1fb04e,0xb927bbed,0x37b73bfc,0x3b022bd9,
0xbbbcba1f,0xb4143927,0x2bd9ba3f,0xbbfcb900,0x3887b593,0xba99bb80,0x3b5a3ad0,0x364eb832,0x38b03c00,0x3a7ca248,0xb97232a1,0x39dc3bd4,0xbbafb534,0x34753b91,0xb75ebbed,0xbb1ab04e,
0x38873bfc,0x3a992bd9,0xb5f13807,0x3b6e3ae9,0xbb80b4d5,0x35933ba0,0xba7cbbaf,0xb8b03475,0xaf0ebad0,0xbbf4b832,0x3a1fa8b6,0xb927bbff,0x3bed39ba,0x304eb996,0x37053bd4,0x3b3032a1,
0x2f0eb972,0xbbf4b9dc,0x3927b115,0xba1fbbe6,0x3bbc3a99,0x3414b887,0x394d3c00,0x39fea248,0xb64e3705,0x3b5a3b30,0xbab5b04e,0x385d3bed,0xbad0bba0,0xb83234d5,0xb6aabbaf,0xbb46b475,
0xb9dca248,0x39723c00,0xbad0b2a1,0x38323bd4,0xb927bbfc,0xba1fabd9,0xb7b7bbbc,0xbb02b414,0x3a5e2f0e,0xb8d8bbf4,0x3b3034d5,0xb705bba0,0x38873be6,0x3a993115,0x364e3b80,0x3b5a3593,
0x3bff3996,0xa8b6b9ba,0x3bc9385d,0xb365bab5,0x2d7e39fe,0x3bf8394d,0x34753ae9,0x3baf3807,0xbbedb900,0x304e3a3f,0xbb91b75e,0x35343b1a,0xb1dbba7c,0xbbddb8b0,0xb5f1bb46,0xbb6eb6aa,
0xba3fbbff,0xb90028b6,0xbbf8ba7c,0xad7e38b0,0x3807b1db,0xbae9bbdd,0xabd9b996,0xbbfcb9ba,0x3b6e3b91,0x35f1b534,0x3bd438d8,0xb2a1ba5e,0xb365375e,0x3bc93b1a,0x35933b02,0x3b8037b7,
0x31db39fe,0x3bdd394d,0x3b5a3bbc,0x364eb414,0xbb46b75e,0x36aa3b1a,0xb11537b7,0x3be63b02,0xb900bbc9,0xba3fb365,0xbbf8b9dc,0x2d7e3972,0x38d8a248,0xba5ebc00,0xb534bab5,0xbb91b85d,
0x3807ad7e,0xbae9bbf8,0xb9febbf4,0xb94daf0e,0x3bdd3b46,0x31dbb6aa,0x35f1b365,0xbb6ebbc9,0x31153996,0x3be639ba,0x3bff3ab5,0x28b6b85d,0xbb02b705,0x37b73b30,0x34d53a5e,0x3ba038d8,
0xbb91b900,0x35343a3f,0x38073b1a,0x3ae9375e,0xb996bbc9,0xb9bab365,0xb887a8b6,0x3a993bff,0x3593b2a1,0xbb80bbd4,0xbbe6bb5a,0xb115364e,0x3bf83a5e,0xad7eb8d8,0xb475b9fe,0xbbafb94d,
0x3b6e3bed,0x35f1b04e,0xb2a1b94d,0xbbd4b9fe,0x31153900,0x3be63a3f,0x39dc34d5,0xb972bba0,0xba1fb593,0x39273b80,0x3baf3bc9,0x3475b365,0xbb91bbdd,0xb53431db,0x34143996,0x3bbc39ba,
0xb75eba7c,0xbb1ab8b0,0xaf0e3593,0x3bf43b80,0x3705a248,0xbb30bc00,0xbae9b85d,0x38073ab5,0x3bdd3a5e,0xb1dbb8d8,0xbb5abbfc,0xb64e2bd9,0x39dc3baf,0x39723475,0xb365b927,0xbbc9ba1f,
0xb36531db,0x3bc93bdd,0x36aa2248,0xbb46bc00,0xbb02b8d8,0x37b73a5e,0x3ba039fe,0xb4d5b94d,0xbb91bbf8,0xb5342d7e,0x3ae93bf4,0x38072f0e,0xb64eb9dc,0xbb5ab972,0x32a138b0,0x3bd43a7c,
0x3a7c385d,0xb8b0bab5,0xb972b5f1,0x39dc3b6e,0x3bf43bbc,0x2f0eb414,0xbbf8bb30,0x2d7e3705,0x394d3b1a,0x39fe375e,0xba5ebbaf,0xb8d8b475,0xa2483593,0x3c003b80,0xb1dbb832,0xbbddbad0,
0xbbf8bbc9,0xad7e3365,0x3b023972,0xb7b7b9dc,0xb9febb5a,0xb94db64e,0x3bed3bdd,0x304eb1db,0xb2a1b807,0xbbd4bae9,0x39ba3b30,0x39963705,0x36aa2f0e,0xbb46bbf4,0x3115375e,0x3be63b1a,
0x39963ae9,0x39ba3807,0xbbddbb30,0x31db3705,0x336537b7,0x3bc93b02,0xbb80bbf8,0xb593ad7e,0xb4d5a8b6,0x3ba03bff,0xb900ba7c,0xba3fb8b0,0xb9feb85d,0x394d3ab5,0xb04eb64e,0xbbedbb5a,
0xabd9b475,0xbbfcbbaf,0x3bed3bf8,0x304ead7e,0x35f13115,0xbb6ebbe6,0x3ab53b80,0x385d3593,0x39dc3887,0xb972ba99,0x38323996,0x3ad039ba,0x3ba03ae9,0xb4d5b807,0x2f0e3534,0x3bf43b91,
0xb8d8b75e,0x3a5e3b1a,0xbb30bbaf,0xb705b475,0xbab5b9dc,0x385d3972,0xb996ba7c,0xb9bab8b0,0xbbc9bb5a,0x3365364e,0xb6aab887,0xbb46ba99,0xbbf4bbfc,0xaf0e2bd9,0xad7eb414,0xbbf8bbbc,
0x3bd43b91,0xb2a1b534,0x39ba3a5e,0x399638d8,0x3bff3bf8,0x28b6ad7e,0x38323900,0x3ad03a3f,0x3baf3be6,0x34753115,0x34d536aa,0x3ba03b46,0x3ae93b5a,0x3807364e,0x2bd931db,0x3bfc3bdd,
0xbb02bb46,0xb7b7b6aa,0xb75eb832,0xbb1abad0,0xba5ebab5,0xb8d8b85d,0xb534b64e,0xbb91bb5a,0xb996b9fe,0xb9bab94d,0xb1dbb414,0xbbddbbbc,0xb8b0b927,0xba7cba1f,0xa8b6af0e,0xbbffbbf4,
0x359335f1,0x3b803b6e,0x311531db,0x3be63bdd,0x34d53534,0x3ba03b91,0x2f0e304e,0x3bf43bed,0x34143475,0x3bbc3baf,0x2bd92d7e,0x3bfc3bf8,0x32a13365,0x3bd43bc9,0x224828b6,0x3c003bff,
0x80000,0x680060,0xc800c0,0x1280120,0xc0004,0x6c0064,0xcc00c4,0x12c0124,0x180010,0x780070,0xd800d0,0x1380130,0x1c0014,0x7c0074,0xdc00d4,0x13c0134,
0x1900188,0x1f001e8,0x2500248,0x2b002a8,0x194018c,0x1f401ec,0x254024c,0x2b402ac,0x1a00198,0x20001f8,0x2600258,0x2c002b8,0x1a4019c,0x20401fc,0x264025c,0x2c402bc,
0x3180310,0x3780370,0x3d803d0,0x4380430,0x31c0314,0x37c0374,0x3dc03d4,0x43c0434,0x3280320,0x3880380,0x3e803e0,0x4480440,0x32c0324,0x38c0384,0x3ec03e4,0x44c0444,
0x4a00498,0x50004f8,0x5600558,0x5c005b8,0x4a4049c,0x50404fc,0x564055c,0x5c405bc,0x4b004a8,0x5100508,0x5700568,0x5d005c8,0x4b404ac,0x514050c,0x574056c,0x5d405cc,
0x6280620,0x6880680,0x6e806e0,0x7480740,0x62c0624,0x68c0684,0x6ec06e4,0x74c0744,0x6380630,0x6980690,0x6f806f0,0x7580750,0x63c0634,0x69c0694,0x6fc06f4,0x75c0754,
0x7b007a8,0x8100808,0x8700868,0x8d008c8,0x7b407ac,0x814080c,0x874086c,0x8d408cc,0x7c007b8,0x8200818,0x8800878,0x8e008d8,0x7c407bc,0x824081c,0x884087c,0x8e408dc,
0x9380930,0x9980990,0x9f809f0,0xa580a50,0x93c0934,0x99c0994,0x9fc09f4,0xa5c0a54,0x9480940,0x9a809a0,0xa080a00,0xa680a60,0x94c0944,0x9ac09a4,0xa0c0a04,0xa6c0a64,
0xac00ab8,0xb200b18,0xb800b78,0xbe00bd8,0xac40abc,0xb240b1c,0xb840b7c,0xbe40bdc,0xad00ac8,0xb300b28,0xb900b88,0xbf00be8,0xad40acc,0xb340b2c,0xb940b8c,0xbf40bec,
0x280020,0x880080,0xe800e0,0x1480140,0x2c0024,0x8c0084,0xec00e4,0x14c0144,0x240020,0x840080,0xe400e0,0x1440140,0x800024,0xe00084,0x14000e4,0x1a80144,
0x1b001a8,0x2100208,0x2700268,0x2d002c8,0x1b401ac,0x214020c,0x274026c,0x2d402cc,0x1ac01a8,0x20c0208,0x26c0268,0x2cc02c8,0x20801ac,0x268020c,0x2c8026c,0x33002cc,
0x3380330,0x3980390,0x3f803f0,0x4580450,0x33c0334,0x39c0394,0x3fc03f4,0x45c0454,0x3340330,0x3940390,0x3f403f0,0x4540450,0x3900334,0x3f00394,0x45003f4,0x4b80454,
0x4c004b8,0x5200518,0x5800578,0x5e005d8,0x4c404bc,0x524051c,0x584057c,0x5e405dc,0x4bc04b8,0x51c0518,0x57c0578,0x5dc05d8,0x51804bc,0x578051c,0x5d8057c,0x64005dc,
0x6480640,0x6a806a0,0x7080700,0x7680760,0x64c0644,0x6ac06a4,0x70c0704,0x76c0764,0x6440640,0x6a406a0,0x7040700,0x7640760,0x6a00644,0x70006a4,0x7600704,0x7c80764,
0x7d007c8,0x8300828,0x8900888,0x8f008e8,0x7d407cc,0x834082c,0x894088c,0x8f408ec,0x7cc07c8,0x82c0828,0x88c0888,0x8ec08e8,0x82807cc,0x888082c,0x8e8088c,0x95008ec,
0x9580950,0x9b809b0,0xa180a10,0xa780a70,0x95c0954,0x9bc09b4,0xa1c0a14,0xa7c0a74,0x9540950,0x9b409b0,0xa140a10,0xa740a70,0x9b00954,0xa1009b4,0xa700a14,0xad80a74,
0xae00ad8,0xb400b38,0xba00b98,0xc000bf8,0xae40adc,0xb440b3c,0xba40b9c,0xc040bfc,0xadc0ad8,0xb3c0b38,0xb9c0b98,0xbfc0bf8,0xb380adc,0xb980b3c,0xbf80b9c,0x300bfc,
0x300030,0x900090,0xf000f0,0x1500150,0x900034,0xf00094,0x15000f4,0x1b80154,0x340030,0x940090,0xf400f0,0x1540150,0x900034,0xf00094,0x15000f4,0x1b80154,
0x1b801b8,0x2180218,0x2780278,0x2d802d8,0x21801bc,0x278021c,0x2d8027c,0x34002dc,0x1bc01b8,0x21c0218,0x27c0278,0x2dc02d8,0x21801bc,0x278021c,0x2d8027c,0x34002dc,
0x3400340,0x3a003a0,0x4000400,0x4600460,0x3a00344,0x40003a4,0x4600404,0x4c80464,0x3440340,0x3a403a0,0x4040400,0x4640460,0x3a00344,0x40003a4,0x4600404,0x4c80464,
0x4c804c8,0x5280528,0x5880588,0x5e805e8,0x52804cc,0x588052c,0x5e8058c,0x65005ec,0x4cc04c8,0x52c0528,0x58c0588,0x5ec05e8,0x52804cc,0x588052c,0x5e8058c,0x65005ec,
0x6500650,0x6b006b0,0x7100710,0x7700770,0x6b00654,0x71006b4,0x7700714,0x7d80774,0x6540650,0x6b406b0,0x7140710,0x7740770,0x6b00654,0x71006b4,0x7700714,0x7d80774,
0x7d807d8,0x8380838,0x8980898,0x8f808f8,0x83807dc,0x898083c,0x8f8089c,0x96008fc,0x7dc07d8,0x83c0838,0x89c0898,0x8fc08f8,0x83807dc,0x898083c,0x8f8089c,0x96008fc,
0x9600960,0x9c009c0,0xa200a20,0xa800a80,0x9c00964,0xa2009c4,0xa800a24,0xae80a84,0x9640960,0x9c409c0,0xa240a20,0xa840a80,0x9c00964,0xa2009c4,0xa800a24,0xae80a84,
0xae80ae8,0xb480b48,0xba80ba8,0xc080c08,0xb480aec,0xba80b4c,0xc080bac,0x380c0c,0xaec0ae8,0xb4c0b48,0xbac0ba8,0xc0c0c08,0xb480aec,0xba80b4c,0xc080bac,0x380c0c,
0x380038,0x980098,0xf800f8,0x1580158,0x98003c,0xf8009c,0x15800fc,0x1c0015c,0x3c0038,0x9c0098,0xfc00f8,0x15c0158,0x98003c,0xf8009c,0x15800fc,0x1c0015c,
0x1c001c0,0x2200220,0x2800280,0x2e002e0,0x22001c4,0x2800224,0x2e00284,0x34802e4,0x1c401c0,0x2240220,0x2840280,0x2e402e0,0x22001c4,0x2800224,0x2e00284,0x34802e4,
0x3480348,0x3a803a8,0x4080408,0x4680468,0x3a8034c,0x40803ac,0x468040c,0x4d0046c,0x34c0348,0x3ac03a8,0x40c0408,0x46c0468,0x3a8034c,0x40803ac,0x468040c,0x4d0046c,
0x4d004d0,0x5300530,0x5900590,0x5f005f0,0x53004d4,0x5900534,0x5f00594,0x65805f4,0x4d404d0,0x5340530,0x5940590,0x5f405f0,0x53004d4,0x5900534,0x5f00594,0x65805f4,
0x6580658,0x6b806b8,0x7180718,0x7780778,0x6b8065c,0x71806bc,0x778071c,0x7e0077c,0x65c0658,0x6bc06b8,0x71c0718,0x77c0778,0x6b8065c,0x71806bc,0x778071c,0x7e0077c,
0x7e007e0,0x8400840,0x8a008a0,0x9000900,0x84007e4,0x8a00844,0x90008a4,0x9680904,0x7e407e0,0x8440840,0x8a408a0,0x9040900,0x84007e4,0x8a00844,0x90008a4,0x9680904,
0x9680968,0x9c809c8,0xa280a28,0xa880a88,0x9c8096c,0xa2809cc,0xa880a2c,0xaf00a8c,0x96c0968,0x9cc09c8,0xa2c0a28,0xa8c0a88,0x9c8096c,0xa2809cc,0xa880a2c,0xaf00a8c,
0xaf00af0,0xb500b50,0xbb00bb0,0xc100c10,0xb500af4,0xbb00b54,0xc100bb4,0x400c14,0xaf40af0,0xb540b50,0xbb40bb0,0xc140c10,0xb500af4,0xbb00b54,0xc100bb4,0x400c14,
0xb040b04,0xb640b64,0xbc40bc4,0xc240c24,0xb640b04,0xbc40bc4,0xc240bc4,0x500050,0xb040b04,0xb640b64,0xbc40bc4,0xc240c24,0xb640b64,0xbc40bc4,0xc240c24,0x500050,
0x97c097c,0x9dc09dc,0xa3c0a3c,0xa9c0a9c,0x9dc097c,0xa3c0a3c,0xa9c0a3c,0xb040b04,0x97c097c,0x9dc09dc,0xa3c0a3c,0xa9c0a9c,0x9dc09dc,0xa3c0a3c,0xa9c0a9c,0xb040b04,
0x7f407f4,0x8540854,0x8b408b4,0x9140914,0x85407f4,0x8b408b4,0x91408b4,0x97c097c,0x7f407f4,0x8540854,0x8b408b4,0x9140914,0x8540854,0x8b408b4,0x9140914,0x97c097c,
0x66c066c,0x6cc06cc,0x72c072c,0x78c078c,0x6cc066c,0x72c072c,0x78c072c,0x7f407f4,0x66c066c,0x6cc06cc,0x72c072c,0x78c078c,0x6cc06cc,0x72c072c,0x78c078c,0x7f407f4,
0x4e404e4,0x5440544,0x5a405a4,0x6040604,0x54404e4,0x5a405a4,0x60405a4,0x66c066c,0x4e404e4,0x5440544,0x5a405a4,0x6040604,0x5440544,0x5a405a4,0x6040604,0x66c066c,
0x35c035c,0x3bc03bc,0x41c041c,0x47c047c,0x3bc035c,0x41c041c,0x47c041c,0x4e404e4,0x35c035c,0x3bc03bc,0x41c041c,0x47c047c,0x3bc03bc,0x41c041c,0x47c047c,0x4e404e4,
0x1d401d4,0x2340234,0x2940294,0x2f402f4,0x23401d4,0x2940294,0x2f40294,0x35c035c,0x1d401d4,0x2340234,0x2940294,0x2f402f4,0x2340234,0x2940294,0x2f402f4,0x35c035c,
0x4c004c,0xac00ac,0x10c010c,0x16c016c,0xac004c,0x10c010c,0x16c010c,0x1d401d4,0x4c004c,0xac00ac,0x10c010c,0x16c016c,0xac00ac,0x10c010c,0x16c016c,0x1d401d4,
0xb000b00,0xb600b60,0xbc00bc0,0xc200c20,0xb600b00,0xbc00bc0,0xc200bc0,0x4c004c,0xb000b00,0xb600b60,0xbc00bc0,0xc200c20,0xb600b60,0xbc00bc0,0xc200c20,0x4c004c,
0x9780978,0x9d809d8,0xa380a38,0xa980a98,0x9d80978,0xa380a38,0xa980a38,0xb000b00,0x9780978,0x9d809d8,0xa380a38,0xa980a98,0x9d809d8,0xa380a38,0xa980a98,0xb000b00,
0x7f007f0,0x8500850,0x8b008b0,0x9100910,0x85007f0,0x8b008b0,0x91008b0,0x9780978,0x7f007f0,0x8500850,0x8b008b0,0x9100910,0x8500850,0x8b008b0,0x9100910,0x9780978,
0x6680668,0x6c806c8,0x7280728,0x7880788,0x6c80668,0x7280728,0x7880728,0x7f007f0,0x6680668,0x6c806c8,0x7280728,0x7880788,0x6c806c8,0x7280728,0x7880788,0x7f007f0,
0x4e004e0,0x5400540,0x5a005a0,0x6000600,0x54004e0,0x5a005a0,0x60005a0,0x6680668,0x4e004e0,0x5400540,0x5a005a0,0x6000600,0x5400540,0x5a005a0,0x6000600,0x6680668,
0x3580358,0x3b803b8,0x4180418,0x4780478,0x3b80358,0x4180418,0x4780418,0x4e004e0,0x3580358,0x3b803b8,0x4180418,0x4780478,0x3b803b8,0x4180418,0x4780478,0x4e004e0,
0x1d001d0,0x2300230,0x2900290,0x2f002f0,0x23001d0,0x2900290,0x2f00290,0x3580358,0x1d001d0,0x2300230,0x2900290,0x2f002f0,0x2300230,0x2900290,0x2f002f0,0x3580358,
0x480048,0xa800a8,0x1080108,0x1680168,0xa80048,0x1080108,0x1680108,0x1d001d0,0x480048,0xa800a8,0x1080108,0x1680168,0xa800a8,0x1080108,0x1680168,0x1d001d0,
0xafc0afc,0xb5c0b5c,0xbbc0bbc,0xc1c0c1c,0xb5c0afc,0xbbc0bbc,0xc1c0bbc,0x480048,0xafc0afc,0xb5c0b5c,0xbbc0bbc,0xc1c0c1c,0xb5c0b5c,0xbbc0bbc,0xc1c0c1c,0x480048,
0x9740974,0x9d409d4,0xa340a34,0xa940a94,0x9d40974,0xa340a34,0xa940a34,0xafc0afc,0x9740974,0x9d409d4,0xa340a34,0xa940a94,0x9d409d4,0xa340a34,0xa940a94,0xafc0afc,
0x7ec07ec,0x84c084c,0x8ac08ac,0x90c090c,0x84c07ec,0x8ac08ac,0x90c08ac,0x9740974,0x7ec07ec,0x84c084c,0x8ac08ac,0x90c090c,0x84c084c,0x8ac08ac,0x90c090c,0x9740974,
0x6640664,0x6c406c4,0x7240724,0x7840784,0x6c40664,0x7240724,0x7840724,0x7ec07ec,0x6640664,0x6c406c4,0x7240724,0x7840784,0x6c406c4,0x7240724,0x7840784,0x7ec07ec,
0x4dc04dc,0x53c053c,0x59c059c,0x5fc05fc,0x53c04dc,0x59c059c,0x5fc059c,0x6640664,0x4dc04dc,0x53c053c,0x59c059c,0x5fc05fc,0x53c053c,0x59c059c,0x5fc05fc,0x6640664,
0x3540354,0x3b403b4,0x4140414,0x4740474,0x3b40354,0x4140414,0x4740414,0x4dc04dc,0x3540354,0x3b403b4,0x4140414,0x4740474,0x3b403b4,0x4140414,0x4740474,0x4dc04dc,
0x1cc01cc,0x22c022c,0x28c028c,0x2ec02ec,0x22c01cc,0x28c028c,0x2ec028c,0x3540354,0x1cc01cc,0x22c022c,0x28c028c,0x2ec02ec,0x22c022c,0x28c028c,0x2ec02ec,0x3540354,
0x440044,0xa400a4,0x1040104,0x1640164,0xa40044,0x1040104,0x1640104,0x1cc01cc,0x440044,0xa400a4,0x1040104,0x1640164,0xa400a4,0x1040104,0x1640164,0x1cc01cc,
0xaf80af8,0xb580b58,0xbb80bb8,0xc180c18,0xb580af8,0xbb80bb8,0xc180bb8,0x440044,0xaf80af8,0xb580b58,0xbb80bb8,0xc180c18,0xb580b58,0xbb80bb8,0xc180c18,0x440044,
0x9700970,0x9d009d0,0xa300a30,0xa900a90,0x9d00970,0xa300a30,0xa900a30,0xaf80af8,0x9700970,0x9d009d0,0xa300a30,0xa900a90,0x9d009d0,0xa300a30,0xa900a90,0xaf80af8,
0x7e807e8,0x8480848,0x8a808a8,0x9080908,0x84807e8,0x8a808a8,0x90808a8,0x9700970,0x7e807e8,0x8480848,0x8a808a8,0x9080908,0x8480848,0x8a808a8,0x9080908,0x9700970,
0x6600660,0x6c006c0,0x7200720,0x7800780,0x6c00660,0x7200720,0x7800720,0x7e807e8,0x6600660,0x6c006c0,0x7200720,0x7800780,0x6c006c0,0x7200720,0x7800780,0x7e807e8,
0x4d804d8,0x5380538,0x5980598,0x5f805f8,0x53804d8,0x5980598,0x5f80598,0x6600660,0x4d804d8,0x5380538,0x5980598,0x5f805f8,0x5380538,0x5980598,0x5f805f8,0x6600660,
0x3500350,0x3b003b0,0x4100410,0x4700470,0x3b00350,0x4100410,0x4700410,0x4d804d8,0x3500350,0x3b003b0,0x4100410,0x4700470,0x3b003b0,0x4100410,0x4700470,0x4d804d8,
0x1c801c8,0x2280228,0x2880288,0x2e802e8,0x22801c8,0x2880288,0x2e80288,0x3500350,0x1c801c8,0x2280228,0x2880288,0x2e802e8,0x2280228,0x2880288,0x2e802e8,0x3500350,
0x400040,0xa000a0,0x1000100,0x1600160,0xa00040,0x1000100,0x1600100,0x1c801c8,0x400040,0xa000a0,0x1000100,0x1600160,0xa000a0,0x1000100,0x1600160,0x1c801c8,
0x30003000,0x30003000,0x30003000,0x30003000,0x30003000,0x30003000,0x30003000,0x30003000,0x0,0x0,0x0,0x0,0x0,0x0,0x0,0x0,
0x30003000,0x30003000,0x30003000,0x30003000,0x30003000,0x30003000,0x30003000,0x30003000,0x0,0x0,0x0,0x0,0x0,0x0,0x0,0x0,
0x2a1f2da8,0xaf64ada8,0xaa1fada8,0x2f642da8,0x2f643000,0xaa1f0000,0xaf64b000,0x2a1f8000,0x2f642da8,0x2a1f2da8,0xaf64ada8,0xaa1fada8,0x2a1f0000,0x2f643000,0xaa1f0000,0xaf64b000,
0x263e2c72,0xafd9aea7,0xa63eac72,0x2fd92ea7,0x2ea72fd9,0xac72a63e,0xaea7afd9,0x2c72263e,0x2fd92ea7,0x263e2c72,0xafd9aea7,0xa63eac72,0x2c72263e,0x2ea72fd9,0xac72a63e,0xaea7afd9,
0x2da80000,0xada80000,0x2da88000,0xada80000,0x2da83000,0xada8b000,0x2da83000,0xada8b000,0x2da83000,0xada8b000,0x2da83000,0xada8b000,0xada80000,0x2da88000,0xada80000,0x2da88000,
0x2f642a1f,0xaf64aa1f,0x2f642a1f,0xaf64aa1f,0x2a1f2f64,0xaa1faf64,0x2a1f2f64,0xaa1faf64,0x2a1f2f64,0xaa1faf64,0x2a1f2f64,0xaa1faf64,0xaf64aa1f,0x2f642a1f,0xaf64aa1f,0x2f642a1f,
0xaa1f2da8,0x2f642da8,0x2a1fada8,0xaf64ada8,0x2f640000,0xaa1fb000,0xaf640000,0x2a1f3000,0xaf64ada8,0xaa1f2da8,0x2f642da8,0x2a1fada8,0x2a1f3000,0x2f648000,0xaa1fb000,0xaf640000,
0xaea7263e,0x2c722fd9,0x2ea7a63e,0xac72afd9,0x2fd92c72,0x263eaea7,0xafd9ac72,0xa63e2ea7,0xac72afd9,0xaea7263e,0x2c722fd9,0x2ea7a63e,0xa63e2ea7,0x2fd92c72,0x263eaea7,0xafd9ac72,
0xada82da8,0xada82da8,0xada82da8,0xada82da8,0x2da8ada8,0x2da8ada8,0x2da8ada8,0x2da8ada8,0x2da82da8,0x2da82da8,0x2da82da8,0x2da82da8,0xada8ada8,0xada8ada8,0xada8ada8,0xada8ada8,
0x3000,0x3000,0x3000,0x80003000,0x8000b000,0x8000b000,0x8000b000,0x8000b000,0x30000000,0x30008000,0x30008000,0x30008000,0xb0000000,0xb0000000,0xb0000000,0xb0000000,
0x2ea7263e,0xac722fd9,0xaea7a63e,0x2c72afd9,0xafd92c72,0xa63eaea7,0x2fd9ac72,0x263e2ea7,0x2c72afd9,0x2ea7263e,0xac722fd9,0xaea7a63e,0x263e2ea7,0xafd92c72,0xa63eaea7,0x2fd9ac72,
0x2f64ada8,0x2a1f2da8,0xaf642da8,0xaa1fada8,0xaa1f3000,0xaf640000,0x2a1fb000,0x2f648000,0xaa1fada8,0x2f64ada8,0x2a1f2da8,0xaf642da8,0x2f640000,0xaa1f3000,0xaf640000,0x2a1fb000,
0xaa1f2f64,0x2a1faf64,0xaa1f2f64,0x2a1faf64,0x2f64aa1f,0xaf642a1f,0x2f64aa1f,0xaf642a1f,0xaf642a1f,0x2f64aa1f,0xaf642a1f,0x2f64aa1f,0xaa1f2f64,0x2a1faf64,0xaa1f2f64,0x2a1faf64,
0x2da80000,0xada80000,0x2da88000,0xada80000,0x2da8b000,0xada83000,0x2da8b000,0xada83000,0xada83000,0x2da8b000,0xada83000,0x2da8b000,0x2da88000,0xada80000,0x2da88000,0xada88000,
0xa63e2c72,0x2fd9aea7,0x263eac72,0xafd92ea7,0xaea72fd9,0x2c72a63e,0x2ea7afd9,0xac72263e,0xafd92ea7,0xa63e2c72,0x2fd9aea7,0x263eac72,0xac72263e,0xaea72fd9,0x2c72a63e,0x2ea7afd9,
0x2f64ada8,0x2a1fada8,0xaf642da8,0xaa1f2da8,0x2a1f0000,0x2f64b000,0xaa1f0000,0xaf643000,0xaa1f2da8,0x2f64ada8,0x2a1fada8,0xaf642da8,0xaf643000,0x2a1f8000,0x2f64b000,0xaa1f8000,
0xb0003000,0xb0003000,0xb0003000,0xb0003000,0xb0003000,0xb0003000,0xb0003000,0xb0003000,0x0,0x8000,0x8000,0x80008000,0x8000,0x8000,0x8000,0x8000,
0x80000000,0x80000000,0x80008000,0x80008000,0x80000000,0x80008000,0x80008000,0x80008000,0xb0003000,0xb0003000,0xb0003000,0xb0003000,0xb0003000,0xb0003000,0xb0003000,0xb0003000,
0xaa1f2da8,0x2f64ada8,0x2a1fada8,0xaf642da8,0xaf643000,0x2a1f0000,0x2f64b000,0xaa1f8000,0xaf642da8,0xaa1f2da8,0x2f64ada8,0x2a1fada8,0xaa1f0000,0xaf643000,0x2a1f0000,0x2f64b000,
0x2fd9aea7,0x263eac72,0xafd92ea7,0xa63e2c72,0x2c72a63e,0x2ea7afd9,0xac72263e,0xaea72fd9,0xa63e2c72,0x2fd9aea7,0x263eac72,0xafd92ea7,0xaea72fd9,0x2c72a63e,0x2ea7afd9,0xac72263e,
0xada80000,0x2da80000,0xada88000,0x2da80000,0xada83000,0x2da8b000,0xada83000,0x2da8b000,0xada83000,0x2da8b000,0xada83000,0x2da8b000,0x2da80000,0xada88000,0x2da88000,0xada88000,
0xaa1f2f64,0x2a1faf64,0xaa1f2f64,0x2a1faf64,0x2f64aa1f,0xaf642a1f,0x2f64aa1f,0xaf642a1f,0x2f64aa1f,0xaf642a1f,0x2f64aa1f,0xaf642a1f,0x2a1faf64,0xaa1f2f64,0x2a1faf64,0xaa1f2f64,
0x2a1f2da8,0xaf642da8,0xaa1fada8,0x2f64ada8,0xaf640000,0x2a1fb000,0x2f640000,0xaa1f3000,0x2f64ada8,0x2a1f2da8,0xaf642da8,0xaa1fada8,0xaa1f3000,0xaf648000,0x2a1fb000,0x2f640000,
0x2c72afd9,0x2ea7263e,0xac722fd9,0xaea7a63e,0x263e2ea7,0xafd92c72,0xa63eaea7,0x2fd9ac72,0xaea7a63e,0x2c72afd9,0x2ea7263e,0xac722fd9,0x2fd9ac72,0x263e2ea7,0xafd92c72,0xa63eaea7,
0x2da8ada8,0x2da8ada8,0x2da8ada8,0x2da8ada8,0xada82da8,0xada82da8,0xada82da8,0xada82da8,0x2da82da8,0x2da82da8,0x2da82da8,0x2da82da8,0xada8ada8,0xada8ada8,0xada8ada8,0xada8ada8,
0x80003000,0x80003000,0x80003000,0x3000,0xb000,0x8000b000,0xb000,0xb000,0xb0000000,0xb0008000,0xb0008000,0xb0008000,0x30000000,0x30000000,0x30000000,0x30008000,
0x2c722fd9,0x2ea7a63e,0xac72afd9,0xaea7263e,0x263eaea7,0xafd9ac72,0xa63e2ea7,0x2fd92c72,0xaea7263e,0x2c722fd9,0x2ea7a63e,0xac72afd9,0x2fd92c72,0x263eaea7,0xafd9ac72,0xa63e2ea7,
0xaf64ada8,0xaa1f2da8,0x2f642da8,0x2a1fada8,0x2a1f3000,0x2f648000,0xaa1fb000,0xaf648000,0x2a1fada8,0xaf64ada8,0xaa1f2da8,0x2f642da8,0xaf640000,0x2a1f3000,0x2f648000,0xaa1fb000,
0x2f642a1f,0xaf64aa1f,0x2f642a1f,0xaf64aa1f,0x2a1f2f64,0xaa1faf64,0x2a1f2f64,0xaa1faf64,0xaa1faf64,0x2a1f2f64,0xaa1faf64,0x2a1f2f64,0x2f642a1f,0xaf64aa1f,0x2f642a1f,0xaf64aa1f,
0xada80000,0x2da80000,0xada88000,0x2da88000,0xada8b000,0x2da83000,0xada8b000,0x2da83000,0x2da83000,0xada8b000,0x2da83000,0xada8b000,0xada88000,0x2da88000,0xada88000,0x2da80000,
0x2fd92ea7,0x263e2c72,0xafd9aea7,0xa63eac72,0x2c72263e,0x2ea72fd9,0xac72a63e,0xaea7afd9,0xa63eac72,0x2fd92ea7,0x263e2c72,0xafd9aea7,0xaea7afd9,0x2c72263e,0x2ea72fd9,0xac72a63e,
0xaf64ada8,0xaa1fada8,0x2f642da8,0x2a1f2da8,0xaa1f0000,0xaf64b000,0x2a1f0000,0x2f643000,0x2a1f2da8,0xaf64ada8,0xaa1fada8,0x2f642da8,0x2f643000,0xaa1f8000,0xaf64b000,0x2a1f0000,
0x80008000,0x80008000,0x80008000,0x80008000,0x80008000,0x80008000,0x80008000,0x80008000,0x30003000,0x30003000,0x30003000,0x30003000,0x30003000,0x30003000,0x30003000,0x30003000,
0x80008000,0x80008000,0x80008000,0x80008000,0x80008000,0x80008000,0x80008000,0x80008000,0x30003000,0x30003000,0x30003000,0x30003000,0x30003000,0x30003000,0x30003000,0x30003000,
0xaf64ada8,0xaa1fada8,0x2f642da8,0x2a1f2da8,0xaa1f8000,0xaf64b000,0x2a1f8000,0x2f643000,0x2a1f2da8,0xaf64ada8,0xaa1fada8,0x2f642da8,0x2f643000,0xaa1f0000,0xaf64b000,0x2a1f8000,
0xafd9aea7,0xa63eac72,0x2fd92ea7,0x263e2c72,0xac72a63e,0xaea7afd9,0x2c72263e,0x2ea72fd9,0x263e2c72,0xafd9aea7,0xa63eac72,0x2fd92ea7,0x2ea72fd9,0xac72a63e,0xaea7afd9,0x2c72263e,
0x2da83000,0xada8b000,0x2da83000,0xada8b000,0xada80000,0x2da88000,0xada80000,0x2da88000,0xada88000,0x2da88000,0xada80000,0x2da88000,0xada8b000,0x2da83000,0xada8b000,0x2da83000,
0x2a1f2f64,0xaa1faf64,0x2a1f2f64,0xaa1faf64,0xaf64aa1f,0x2f642a1f,0xaf64aa1f,0x2f642a1f,0xaf64aa1f,0x2f642a1f,0xaf64aa1f,0x2f642a1f,0xaa1faf64,0x2a1f2f64,0xaa1faf64,0x2a1f2f64,
0xaf64ada8,0xaa1f2da8,0x2f642da8,0x2a1fada8,0x2a1f3000,0x2f648000,0xaa1fb000,0xaf640000,0x2a1fada8,0xaf64ada8,0xaa1f2da8,0x2f642da8,0xaf648000,0x2a1f3000,0x2f648000,0xaa1fb000,
0xac72afd9,0xaea7263e,0x2c722fd9,0x2ea7a63e,0xa63e2ea7,0x2fd92c72,0x263eaea7,0xafd9ac72,0x2ea7a63e,0xac72afd9,0xaea7263e,0x2c722fd9,0xafd9ac72,0xa63e2ea7,0x2fd92c72,0x263eaea7,
0xada8ada8,0xada8ada8,0xada8ada8,0xada8ada8,0x2da82da8,0x2da82da8,0x2da82da8,0x2da82da8,0xada82da8,0xada82da8,0xada82da8,0xada82da8,0x2da8ada8,0x2da8ada8,0x2da8ada8,0x2da8ada8,
0xb0008000,0xb0000000,0xb0000000,0xb0000000,0x30008000,0x30008000,0x30008000,0x30008000,0x3000,0x3000,0x3000,0x80003000,0x8000b000,0x8000b000,0x8000b000,0x8000b000,
0xac722fd9,0xaea7a63e,0x2c72afd9,0x2ea7263e,0xa63eaea7,0x2fd9ac72,0x263e2ea7,0xafd92c72,0x2ea7263e,0xac722fd9,0xaea7a63e,0x2c72afd9,0xafd92c72,0xa63eaea7,0x2fd9ac72,0x263e2ea7,
0x2a1f2da8,0xaf642da8,0xaa1fada8,0x2f64ada8,0xaf648000,0x2a1fb000,0x2f648000,0xaa1f3000,0x2f64ada8,0x2a1f2da8,0xaf642da8,0xaa1fada8,0xaa1f3000,0xaf640000,0x2a1fb000,0x2f648000,
0xaf642a1f,0x2f64aa1f,0xaf642a1f,0x2f64aa1f,0xaa1f2f64,0x2a1faf64,0xaa1f2f64,0x2a1faf64,0x2a1faf64,0xaa1f2f64,0x2a1faf64,0xaa1f2f64,0xaf642a1f,0x2f64aa1f,0xaf642a1f,0x2f64aa1f,
0xada83000,0x2da8b000,0xada83000,0x2da8b000,0x2da88000,0xada80000,0x2da88000,0xada88000,0xada88000,0x2da88000,0xada80000,0x2da88000,0xada83000,0x2da8b000,0xada83000,0x2da8b000,
0xafd92ea7,0xa63e2c72,0x2fd9aea7,0x263eac72,0xac72263e,0xaea72fd9,0x2c72a63e,0x2ea7afd9,0x263eac72,0xafd92ea7,0xa63e2c72,0x2fd9aea7,0x2ea7afd9,0xac72263e,0xaea72fd9,0x2c72a63e,
0xaa1f2da8,0x2f64ada8,0x2a1fada8,0xaf642da8,0xaf643000,0x2a1f8000,0x2f64b000,0xaa1f8000,0xaf642da8,0xaa1f2da8,0x2f64ada8,0x2a1fada8,0xaa1f8000,0xaf643000,0x2a1f8000,0x2f64b000,
0x80008000,0x80000000,0x80000000,0x0,0x80000000,0x80000000,0x80000000,0x80000000,0xb0003000,0xb0003000,0xb0003000,0xb0003000,0xb0003000,0xb0003000,0xb0003000,0xb0003000,
0x3000b000,0x3000b000,0x3000b000,0x3000b000,0x3000b000,0x3000b000,0x3000b000,0x3000b000,0x80000000,0x80000000,0x80008000,0x80008000,0x80000000,0x80008000,0x80008000,0x80008000,
0x2f64ada8,0x2a1fada8,0xaf642da8,0xaa1f2da8,0x2a1f8000,0x2f64b000,0xaa1f8000,0xaf643000,0xaa1f2da8,0x2f64ada8,0x2a1fada8,0xaf642da8,0xaf643000,0x2a1f0000,0x2f64b000,0xaa1f8000,
0x263eac72,0xafd92ea7,0xa63e2c72,0x2fd9aea7,0x2ea7afd9,0xac72263e,0xaea72fd9,0x2c72a63e,0x2fd9aea7,0x263eac72,0xafd92ea7,0xa63e2c72,0x2c72a63e,0x2ea7afd9,0xac72263e,0xaea72fd9,
0xada83000,0x2da8b000,0xada83000,0x2da8b000,0x2da80000,0xada88000,0x2da88000,0xada88000,0x2da88000,0xada88000,0x2da80000,0xada88000,0x2da8b000,0xada83000,0x2da8b000,0xada83000,
0x2f64aa1f,0xaf642a1f,0x2f64aa1f,0xaf642a1f,0x2a1faf64,0xaa1f2f64,0x2a1faf64,0xaa1f2f64,0x2a1faf64,0xaa1f2f64,0x2a1faf64,0xaa1f2f64,0xaf642a1f,0x2f64aa1f,0xaf642a1f,0x2f64aa1f,
0x2f64ada8,0x2a1f2da8,0xaf642da8,0xaa1fada8,0xaa1f3000,0xaf648000,0x2a1fb000,0x2f640000,0xaa1fada8,0x2f64ada8,0x2a1f2da8,0xaf642da8,0x2f648000,0xaa1f3000,0xaf648000,0x2a1fb000,
0xaea7a63e,0x2c72afd9,0x2ea7263e,0xac722fd9,0x2fd9ac72,0x263e2ea7,0xafd92c72,0xa63eaea7,0xac722fd9,0xaea7a63e,0x2c72afd9,0x2ea7263e,0xa63eaea7,0x2fd9ac72,0x263e2ea7,0xafd92c72,
0xada8ada8,0xada8ada8,0xada8ada8,0xada8ada8,0x2da82da8,0x2da82da8,0x2da82da8,0x2da82da8,0x2da8ada8,0x2da8ada8,0x2da8ada8,0x2da8ada8,0xada82da8,0xada82da8,0xada82da8,0xada82da8,
0x30008000,0x30000000,0x30000000,0x30000000,0xb0008000,0xb0008000,0xb0008000,0xb0000000,0x80003000,0x80003000,0x80003000,0x3000,0xb000,0x8000b000,0xb000,0xb000,
0x2ea7a63e,0xac72afd9,0xaea7263e,0x2c722fd9,0xafd9ac72,0xa63e2ea7,0x2fd92c72,0x263eaea7,0x2c722fd9,0x2ea7a63e,0xac72afd9,0xaea7263e,0x263eaea7,0xafd9ac72,0xa63e2ea7,0x2fd92c72,
0xaa1f2da8,0x2f642da8,0x2a1fada8,0xaf64ada8,0x2f648000,0xaa1fb000,0xaf640000,0x2a1f3000,0xaf64ada8,0xaa1f2da8,0x2f642da8,0x2a1fada8,0x2a1f3000,0x2f648000,0xaa1fb000,0xaf648000,
0xaa1faf64,0x2a1f2f64,0xaa1faf64,0x2a1f2f64,0x2f642a1f,0xaf64aa1f,0x2f642a1f,0xaf64aa1f,0xaf64aa1f,0x2f642a1f,0xaf64aa1f,0x2f642a1f,0xaa1faf64,0x2a1f2f64,0xaa1faf64,0x2a1f2f64,
0x2da83000,0xada8b000,0x2da83000,0xada8b000,0xada88000,0x2da88000,0xada88000,0x2da80000,0x2da88000,0xada88000,0x2da80000,0xada80000,0x2da83000,0xada8b000,0x2da83000,0xada8b000,
0xa63eac72,0x2fd92ea7,0x263e2c72,0xafd9aea7,0xaea7afd9,0x2c72263e,0x2ea72fd9,0xac72a63e,0xafd9aea7,0xa63eac72,0x2fd92ea7,0x263e2c72,0xac72a63e,0xaea7afd9,0x2c72263e,0x2ea72fd9,
0x2a1f2da8,0xaf64ada8,0xaa1fada8,0x2f642da8,0x2f643000,0xaa1f8000,0xaf64b000,0x2a1f0000,0x2f642da8,0x2a1f2da8,0xaf64ada8,0xaa1fada8,0x2a1f8000,0x2f643000,0xaa1f8000,0xaf64b000,
0x3c003c00,0x3c003c00,0x3c003c00,0x3c003c00,0x3c003c00,0x3c003c00,0x3c003c00,0x3c003c00,0x80008000,0x80008000,0x80008000,0x80008000,0x80008000,0x80008000,0x80008000,0x80008000,
0x3bd93c00,0x3aa73b64,0x387239a8,0x323e361f,0xb23e0000,0xb872b61f,0xbaa7b9a8,0xbbd9bb64,0xb23e8000,0xb872b61f,0xbaa7b9a8,0xbbd9bb64,0xbbd9bc00,0xbaa7bb64,0xb872b9a8,0xb23eb61f,
0xbb64bc00,0xb61fb9a8,0x361f8000,0x3b6439a8,0x3b643c00,0x361f39a8,0xb61f0000,0xbb64b9a8,0x361f8000,0x3b6439a8,0x3b643c00,0x361f39a8,0xb61f8000,0xbb64b9a8,0xbb64bc00,0xb61fb9a8,
0x38728000,0x3bd93b64,0x323e39a8,0xbaa7b61f,0x3aa73c00,0xb23e361f,0xbbd9b9a8,0xb872bb64,0x3aa73c00,0xb23e361f,0xbbd9b9a8,0xb872bb64,0xb8728000,0xbbd9bb64,0xb23eb9a8,0x3aa7361f,
0xbc008000,0x3c008000,0xbc000000,0x3c008000,0xbc000000,0x3c008000,0xbc000000,0x3c008000,0x3c00,0x8000bc00,0x3c00,0x8000bc00,0x3c00,0x8000bc00,0x80003c00,0x8000bc00,
0xbbd98000,0x3aa7361f,0xb872b9a8,0x323e3b64,0x323ebc00,0xb8723b64,0x3aa7b9a8,0xbbd9361f,0xb23e3c00,0x3872bb64,0xbaa739a8,0x3bd9b61f,0xbbd90000,0x3aa7361f,0xb872b9a8,0x323e3b64,
0x3b648000,0xb61fb9a8,0xb61f3c00,0x3b64b9a8,0xbb648000,0x361f39a8,0x361fbc00,0xbb6439a8,0x361fbc00,0xbb6439a8,0x3b648000,0xb61fb9a8,0xb61f3c00,0x3b64b9a8,0xbb640000,0x361f39a8,
0xb8723c00,0x3bd9b61f,0xb23eb9a8,0xbaa73b64,0xbaa78000,0xb23e3b64,0x3bd9b9a8,0xb872b61f,0x3aa78000,0x323ebb64,0xbbd939a8,0x3872361f,0xb8723c00,0x3bd9b61f,0xb23eb9a8,0xbaa73b64,
0xbbd93c00,0xbaa73b64,0xb87239a8,0xb23e361f,0x323e8000,0x3872b61f,0x3aa7b9a8,0x3bd9bb64,0x323e8000,0x3872b61f,0x3aa7b9a8,0x3bd9bb64,0x3bd9bc00,0x3aa7bb64,0x3872b9a8,0x323eb61f,
0xbc003c00,0xbc003c00,0xbc003c00,0xbc003c00,0xbc003c00,0xbc003c00,0xbc003c00,0xbc003c00,0x80008000,0x80000000,0x80000000,0x80000000,0x80000000,0x80000000,0x0,0x80000000,
0xb8728000,0xbbd93b64,0xb23e39a8,0x3aa7b61f,0xbaa73c00,0x323e361f,0x3bd9b9a8,0x3872bb64,0xbaa73c00,0x323e361f,0x3bd9b9a8,0x3872bb64,0x38728000,0x3bd9bb64,0x323eb9a8,0xbaa7361f,
0x3b64bc00,0x361fb9a8,0xb61f8000,0xbb6439a8,0xbb643c00,0xb61f39a8,0x361f0000,0x3b64b9a8,0xb61f8000,0xbb6439a8,0xbb643c00,0xb61f39a8,0x361f8000,0x3b64b9a8,0x3b64bc00,0x361fb9a8,
0x3bd98000,0xbaa7361f,0x3872b9a8,0xb23e3b64,0xb23ebc00,0x38723b64,0xbaa7b9a8,0x3bd9361f,0x323e3c00,0xb872bb64,0x3aa739a8,0xbbd9b61f,0x3bd98000,0xbaa7361f,0x3872b9a8,0xb23e3b64,
0x3c008000,0xbc008000,0x3c000000,0xbc008000,0x3c000000,0xbc008000,0x3c000000,0xbc000000,0x80003c00,0xbc00,0x80003c00,0x8000bc00,0x80003c00,0xbc00,0x80003c00,0xbc00,
0x38723c00,0xbbd9b61f,0x323eb9a8,0x3aa73b64,0x3aa78000,0x323e3b64,0xbbd9b9a8,0x3872b61f,0xbaa78000,0xb23ebb64,0x3bd939a8,0xb872361f,0x38723c00,0xbbd9b61f,0x323eb9a8,0x3aa73b64,
0xbb640000,0x361fb9a8,0x361f3c00,0xbb64b9a8,0x3b648000,0xb61f39a8,0xb61fbc00,0x3b6439a8,0xb61fbc00,0x3b6439a8,0xbb640000,0x361fb9a8,0x361f3c00,0xbb64b9a8,0x3b648000,0xb61f39a8,
0x39a83c00,0xb9a80000,0xb9a8bc00,0x39a88000,0x39a83c00,0xb9a80000,0xb9a8bc00,0x39a88000,0xb9a88000,0xb9a8bc00,0x39a88000,0x39a83c00,0xb9a80000,0xb9a8bc00,0x39a88000,0x39a83c00,
0x38723c00,0xbbd9b61f,0x323eb9a8,0x3aa73b64,0xbaa70000,0xb23ebb64,0x3bd939a8,0xb872361f,0xbaa78000,0xb23ebb64,0x3bd939a8,0xb872361f,0xb872bc00,0x3bd9361f,0xb23e39a8,0xbaa7bb64,
0xb61fbc00,0x3b6439a8,0xbb640000,0x361fb9a8,0x361f3c00,0xbb64b9a8,0x3b648000,0xb61f39a8,0x3b648000,0xb61f39a8,0xb61fbc00,0x3b6439a8,0xbb648000,0x361fb9a8,0x361f3c00,0xbb64b9a8,
0x3bd98000,0xbaa7361f,0x3872b9a8,0xb23e3b64,0x323e3c00,0xb872bb64,0x3aa739a8,0xbbd9b61f,0x323e3c00,0xb872bb64,0x3aa739a8,0xbbd9b61f,0xbbd98000,0x3aa7b61f,0xb87239a8,0x323ebb64,
0xb9a88000,0xb9a83c00,0x39a88000,0x39a8bc00,0xb9a80000,0xb9a83c00,0x39a88000,0x39a8bc00,0xb9a83c00,0x39a88000,0x39a8bc00,0xb9a80000,0xb9a83c00,0x39a88000,0x39a8bc00,0xb9a88000,
0xb8728000,0xbbd93b64,0xb23e39a8,0x3aa7b61f,0x3aa7bc00,0xb23eb61f,0xbbd939a8,0xb8723b64,0xbaa73c00,0x323e361f,0x3bd9b9a8,0x3872bb64,0xb8728000,0xbbd93b64,0xb23e39a8,0x3aa7b61f,
0x361f8000,0x3b64b9a8,0x3b64bc00,0x361fb9a8,0xb61f8000,0xbb6439a8,0xbb643c00,0xb61f39a8,0x3b64bc00,0x361fb9a8,0xb61f8000,0xbb6439a8,0xbb643c00,0xb61f39a8,0x361f8000,0x3b64b9a8,
0xbbd93c00,0xbaa73b64,0xb87239a8,0xb23e361f,0xb23e8000,0xb872361f,0xbaa739a8,0xbbd93b64,0x323e8000,0x3872b61f,0x3aa7b9a8,0x3bd9bb64,0xbbd93c00,0xbaa73b64,0xb87239a8,0xb23e361f,
0xb8723c00,0x3bd9b61f,0xb23eb9a8,0xbaa73b64,0x3aa78000,0x323ebb64,0xbbd939a8,0x3872361f,0x3aa78000,0x323ebb64,0xbbd939a8,0x3872361f,0x3872bc00,0xbbd9361f,0x323e39a8,0x3aa7bb64,
0xb9a83c00,0x39a80000,0x39a8bc00,0xb9a88000,0xb9a83c00,0x39a88000,0x39a8bc00,0xb9a88000,0x39a88000,0x39a8bc00,0xb9a88000,0xb9a83c00,0x39a80000,0x39a8bc00,0xb9a88000,0xb9a83c00,
0xbbd98000,0x3aa7361f,0xb872b9a8,0x323e3b64,0xb23e3c00,0x3872bb64,0xbaa739a8,0x3bd9b61f,0xb23e3c00,0x3872bb64,0xbaa739a8,0x3bd9b61f,0x3bd98000,0xbaa7b61f,0x387239a8,0xb23ebb64,
0x361fbc00,0xbb6439a8,0x3b640000,0xb61fb9a8,0xb61f3c00,0x3b64b9a8,0xbb648000,0x361f39a8,0xbb648000,0x361f39a8,0x361fbc00,0xbb6439a8,0x3b648000,0xb61fb9a8,0xb61f3c00,0x3b64b9a8,
0x38728000,0x3bd93b64,0x323e39a8,0xbaa7b61f,0xbaa7bc00,0x323eb61f,0x3bd939a8,0x38723b64,0x3aa73c00,0xb23e361f,0xbbd9b9a8,0xb872bb64,0x38728000,0x3bd93b64,0x323e39a8,0xbaa7b61f,
0x39a88000,0x39a83c00,0xb9a88000,0xb9a8bc00,0x39a80000,0x39a83c00,0xb9a80000,0xb9a8bc00,0x39a83c00,0xb9a88000,0xb9a8bc00,0x39a88000,0x39a83c00,0xb9a88000,0xb9a8bc00,0x39a80000,
0x3bd93c00,0x3aa73b64,0x387239a8,0x323e361f,0x323e8000,0x3872361f,0x3aa739a8,0x3bd93b64,0xb23e8000,0xb872b61f,0xbaa7b9a8,0xbbd9bb64,0x3bd93c00,0x3aa73b64,0x387239a8,0x323e361f,
0xb61f8000,0xbb64b9a8,0xbb64bc00,0xb61fb9a8,0x361f8000,0x3b6439a8,0x3b643c00,0x361f39a8,0xbb64bc00,0xb61fb9a8,0x361f0000,0x3b6439a8,0x3b643c00,0x361f39a8,0xb61f8000,0xbb64b9a8,
0x0,0x0,0x0,0x0,0x0,0x0,0x0,0x0,0x3c003c00,0x3c003c00,0x3c003c00,0x3c003c00,0x3c003c00,0x3c003c00,0x3c003c00,0x3c003c00,
0x323e0000,0x3872361f,0x3aa739a8,0x3bd93b64,0x3bd93c00,0x3aa73b64,0x387239a8,0x323e361f,0x3bd93c00,0x3aa73b64,0x387239a8,0x323e361f,0xb23e0000,0xb872b61f,0xbaa7b9a8,0xbbd9bb64,
0xb61f0000,0xbb64b9a8,0xbb64bc00,0xb61fb9a8,0x361f0000,0x3b6439a8,0x3b643c00,0x361f39a8,0xbb64bc00,0xb61fb9a8,0x361f8000,0x3b6439a8,0x3b643c00,0x361f39a8,0xb61f0000,0xbb64b9a8,
0xbaa7bc00,0x323eb61f,0x3bd939a8,0x38723b64,0x38720000,0x3bd93b64,0x323e39a8,0xbaa7b61f,0x38728000,0x3bd93b64,0x323e39a8,0xbaa7b61f,0x3aa73c00,0xb23e361f,0xbbd9b9a8,0xb872bb64,
0x3c00,0x8000bc00,0x3c00,0x8000bc00,0x3c00,0x8000bc00,0x80003c00,0x8000bc00,0x3c000000,0xbc000000,0x3c008000,0xbc000000,0x3c008000,0xbc000000,0x3c008000,0xbc000000,
0xb23e3c00,0x3872bb64,0xbaa739a8,0x3bd9b61f,0xbbd90000,0x3aa7361f,0xb872b9a8,0x323e3b64,0x3bd90000,0xbaa7b61f,0x387239a8,0xb23ebb64,0xb23e3c00,0x3872bb64,0xbaa739a8,0x3bd9b61f,
0x361fbc00,0xbb6439a8,0x3b648000,0xb61fb9a8,0xb61f3c00,0x3b64b9a8,0xbb640000,0x361f39a8,0xbb640000,0x361f39a8,0x361fbc00,0xbb6439a8,0x3b640000,0xb61fb9a8,0xb61f3c00,0x3b64b9a8,
0x3aa78000,0x323ebb64,0xbbd939a8,0x3872361f,0xb8723c00,0x3bd9b61f,0xb23eb9a8,0xbaa73b64,0x3872bc00,0xbbd9361f,0x323e39a8,0x3aa7bb64,0x3aa70000,0x323ebb64,0xbbd939a8,0x3872361f,
0xb23e0000,0xb872361f,0xbaa739a8,0xbbd93b64,0xbbd93c00,0xbaa73b64,0xb87239a8,0xb23e361f,0xbbd93c00,0xbaa73b64,0xb87239a8,0xb23e361f,0x323e8000,0x3872b61f,0x3aa7b9a8,0x3bd9bb64,
0x0,0x8000,0x8000,0x8000,0x8000,0x8000,0x80008000,0x8000,0xbc003c00,0xbc003c00,0xbc003c00,0xbc003c00,0xbc003c00,0xbc003c00,0xbc003c00,0xbc003c00,
0x3aa7bc00,0xb23eb61f,0xbbd939a8,0xb8723b64,0xb8720000,0xbbd93b64,0xb23e39a8,0x3aa7b61f,0xb8728000,0xbbd93b64,0xb23e39a8,0x3aa7b61f,0xbaa73c00,0x323e361f,0x3bd9b9a8,0x3872bb64,
0x361f0000,0x3b64b9a8,0x3b64bc00,0x361fb9a8,0xb61f0000,0xbb6439a8,0xbb643c00,0xb61f39a8,0x3b64bc00,0x361fb9a8,0xb61f8000,0xbb6439a8,0xbb643c00,0xb61f39a8,0x361f0000,0x3b64b9a8,
0x323e3c00,0xb872bb64,0x3aa739a8,0xbbd9b61f,0x3bd98000,0xbaa7361f,0x3872b9a8,0xb23e3b64,0xbbd90000,0x3aa7b61f,0xb87239a8,0x323ebb64,0x323e3c00,0xb872bb64,0x3aa739a8,0xbbd9b61f,
0x80003c00,0xbc00,0x80003c00,0x8000bc00,0x80003c00,0xbc00,0x80003c00,0xbc00,0xbc000000,0x3c000000,0xbc008000,0x3c000000,0xbc008000,0x3c000000,0xbc008000,0x3c008000,
0xbaa78000,0xb23ebb64,0x3bd939a8,0xb872361f,0x38723c00,0xbbd9b61f,0x323eb9a8,0x3aa73b64,0xb872bc00,0x3bd9361f,0xb23e39a8,0xbaa7bb64,0xbaa70000,0xb23ebb64,0x3bd939a8,0xb872361f,
0xb61fbc00,0x3b6439a8,0xbb640000,0x361fb9a8,0x361f3c00,0xbb64b9a8,0x3b648000,0xb61f39a8,0x3b648000,0xb61f39a8,0xb61fbc00,0x3b6439a8,0xbb640000,0x361fb9a8,0x361f3c00,0xbb64b9a8,
0x39a80000,0x39a83c00,0xb9a80000,0xb9a8bc00,0x39a88000,0x39a83c00,0xb9a80000,0xb9a8bc00,0x39a83c00,0xb9a80000,0xb9a8bc00,0x39a88000,0x39a83c00,0xb9a80000,0xb9a8bc00,0x39a88000,
0x3aa70000,0x323e3b64,0xbbd9b9a8,0x3872b61f,0x38723c00,0xbbd9b61f,0x323eb9a8,0x3aa73b64,0x38723c00,0xbbd9b61f,0x323eb9a8,0x3aa73b64,0xbaa70000,0xb23ebb64,0x3bd939a8,0xb872361f,
0xbb640000,0x361fb9a8,0x361f3c00,0xbb64b9a8,0x3b640000,0xb61f39a8,0xb61fbc00,0x3b6439a8,0xb61fbc00,0x3b6439a8,0xbb640000,0x361fb9a8,0x361f3c00,0xbb64b9a8,0x3b648000,0xb61f39a8,
0xb23ebc00,0x38723b64,0xbaa7b9a8,0x3bd9361f,0x3bd90000,0xbaa7361f,0x3872b9a8,0xb23e3b64,0x3bd98000,0xbaa7361f,0x3872b9a8,0xb23e3b64,0x323e3c00,0xb872bb64,0x3aa739a8,0xbbd9b61f,
0xb9a83c00,0x39a88000,0x39a8bc00,0xb9a80000,0xb9a83c00,0x39a88000,0x39a8bc00,0xb9a88000,0x39a80000,0x39a8bc00,0xb9a80000,0xb9a83c00,0x39a88000,0x39a8bc00,0xb9a80000,0xb9a83c00,
0xbaa73c00,0x323e361f,0x3bd9b9a8,0x3872bb64,0xb8728000,0xbbd93b64,0xb23e39a8,0x3aa7b61f,0x38720000,0x3bd9bb64,0x323eb9a8,0xbaa7361f,0xbaa73c00,0x323e361f,0x3bd9b9a8,0x3872bb64,
0x3b64bc00,0x361fb9a8,0xb61f8000,0xbb6439a8,0xbb643c00,0xb61f39a8,0x361f8000,0x3b64b9a8,0xb61f0000,0xbb6439a8,0xbb643c00,0xb61f39a8,0x361f0000,0x3b64b9a8,0x3b64bc00,0x361fb9a8,
0x323e8000,0x3872b61f,0x3aa7b9a8,0x3bd9bb64,0xbbd93c00,0xbaa73b64,0xb87239a8,0xb23e361f,0x3bd9bc00,0x3aa7bb64,0x3872b9a8,0x323eb61f,0x323e0000,0x3872b61f,0x3aa7b9a8,0x3bd9bb64,
0xbaa70000,0xb23e3b64,0x3bd9b9a8,0xb872b61f,0xb8723c00,0x3bd9b61f,0xb23eb9a8,0xbaa73b64,0xb8723c00,0x3bd9b61f,0xb23eb9a8,0xbaa73b64,0x3aa78000,0x323ebb64,0xbbd939a8,0x3872361f,
0xb9a80000,0xb9a83c00,0x39a80000,0x39a8bc00,0xb9a88000,0xb9a83c00,0x39a80000,0x39a8bc00,0xb9a83c00,0x39a80000,0x39a8bc00,0xb9a88000,0xb9a83c00,0x39a88000,0x39a8bc00,0xb9a88000,
0x323ebc00,0xb8723b64,0x3aa7b9a8,0xbbd9361f,0xbbd90000,0x3aa7361f,0xb872b9a8,0x323e3b64,0xbbd98000,0x3aa7361f,0xb872b9a8,0x323e3b64,0xb23e3c00,0x3872bb64,0xbaa739a8,0x3bd9b61f,
0x3b640000,0xb61fb9a8,0xb61f3c00,0x3b64b9a8,0xbb640000,0x361f39a8,0x361fbc00,0xbb6439a8,0x361fbc00,0xbb6439a8,0x3b640000,0xb61fb9a8,0xb61f3c00,0x3b64b9a8,0xbb648000,0x361f39a8,
0x3aa73c00,0xb23e361f,0xbbd9b9a8,0xb872bb64,0x38728000,0x3bd93b64,0x323e39a8,0xbaa7b61f,0xb8720000,0xbbd9bb64,0xb23eb9a8,0x3aa7361f,0x3aa73c00,0xb23e361f,0xbbd9b9a8,0xb872bb64,
0x39a83c00,0xb9a88000,0xb9a8bc00,0x39a88000,0x39a83c00,0xb9a88000,0xb9a8bc00,0x39a80000,0xb9a80000,0xb9a8bc00,0x39a80000,0x39a83c00,0xb9a88000,0xb9a8bc00,0x39a88000,0x39a83c00,
0xb23e8000,0xb872b61f,0xbaa7b9a8,0xbbd9bb64,0x3bd93c00,0x3aa73b64,0x387239a8,0x323e361f,0xbbd9bc00,0xbaa7bb64,0xb872b9a8,0xb23eb61f,0xb23e0000,0xb872b61f,0xbaa7b9a8,0xbbd9bb64,
0xbb64bc00,0xb61fb9a8,0x361f0000,0x3b6439a8,0x3b643c00,0x361f39a8,0xb61f8000,0xbb64b9a8,0x361f0000,0x3b6439a8,0x3b643c00,0x361f39a8,0xb61f0000,0xbb64b9a8,0xbb64bc00,0xb61fb9a8,
};
__device__ __align__(1024) bf16 g_x1T[DM * XP];
__device__ __align__(1024) bf16 g_x2T[DM * XP];
constexpr int FP = SEQ + 32;
__device__ __align__(1024) uint32_t g_fin[DM / 2][FP];
__device__ __align__(1024) float g_sums[2][2][SEQ];

#define TS_DECL
#define TS_ARG
#define TS_PASS
#define TS_PHASE(p)
#define TS(i)
#define TSX(row, i)
#define TS_BEGIN
#define TS_END

__device__ __align__(1024) uint32_t g_keo[DM / 2][2048];
__device__ __align__(128) uint32_t g_ksc[DM];

struct cplx { float r, i; };
__device__ __forceinline__ cplx cmul(cplx a, cplx b) {
    cplx o;
    o.r = fmaf(a.r, b.r, -a.i * b.i);
    o.i = fmaf(a.r, b.i, a.i * b.r);
    return o;
}
__device__ __forceinline__ cplx csq(cplx a) {
    cplx o;
    o.r = fmaf(a.r, a.r, -a.i * a.i);
    o.i = 2.f * a.r * a.i;
    return o;
}
__device__ __forceinline__ cplx cexp_p(float arl, float ai, float p) {
    float mag = ex2(arl * p);
    float ang = ai * p;
    float n = rintf(ang * 0.15915494309189535f);
    float r = fmaf(n, -6.2831854820251465f, ang);
    r = fmaf(n, 1.7484555e-7f, r);
    cplx o;
    o.r = mag * __cosf(r);
    o.i = mag * __sinf(r);
    return o;
}

__device__ __forceinline__ uint32_t pack2h(float lo, float hi) {
    uint32_t r;
    asm("cvt.rn.f16x2.f32 %0, %1, %2;" : "=r"(r) : "f"(hi), "f"(lo));
    return r;
}
__device__ __forceinline__ uint32_t hmul(uint32_t a, uint32_t b) { uint32_t d; asm("mul.rn.f16x2 %0, %1, %2;" : "=r"(d) : "r"(a), "r"(b)); return d; }
__device__ __forceinline__ uint32_t hfma(uint32_t a, uint32_t b, uint32_t c) { uint32_t d; asm("fma.rn.f16x2 %0, %1, %2, %3;" : "=r"(d) : "r"(a), "r"(b), "r"(c)); return d; }
__device__ __forceinline__ uint32_t hfms(uint32_t a, uint32_t b, uint32_t c) {
    uint32_t d;
    asm("{\n.reg .b32 n;\nneg.f16x2 n, %1;\nfma.rn.f16x2 %0, n, %2, %3;\n}" : "=r"(d) : "r"(a), "r"(b), "r"(c));
    return d;
}
__device__ __forceinline__ uint32_t hadd(uint32_t a, uint32_t b) { uint32_t d; asm("add.rn.f16x2 %0, %1, %2;" : "=r"(d) : "r"(a), "r"(b)); return d; }
__device__ __forceinline__ uint32_t hsub(uint32_t a, uint32_t b) { uint32_t d; asm("sub.rn.f16x2 %0, %1, %2;" : "=r"(d) : "r"(a), "r"(b)); return d; }
__device__ __forceinline__ uint4 ldg_tab(int tab, int t) {
    uint4 v;
    asm volatile("ld.global.nc.v4.u32 {%0,%1,%2,%3}, [%4];" : "=r"(v.x), "=r"(v.y), "=r"(v.z), "=r"(v.w) : "l"((const uint4*)c_fft + tab * 128 + t));
    return v;
}
__device__ __forceinline__ uint32_t u4(const uint4& v, int i) { return i == 0 ? v.x : i == 1 ? v.y : i == 2 ? v.z : v.w; }
struct cpair { uint32_t r, i; };
__device__ __forceinline__ cpair pmul(cpair p, uint32_t z) {
    const __half2 zv = *reinterpret_cast<const __half2*>(&z), pr = *reinterpret_cast<const __half2*>(&p.r), pi = *reinterpret_cast<const __half2*>(&p.i);
    const __half2 zr = __low2half2(zv), zi = __high2half2(zv);
    const __half2 a = __hfma2(__hneg2(pi), zi, __hmul2(pr, zr)), b = __hfma2(pi, zr, __hmul2(pr, zi));
    return {*reinterpret_cast<const uint32_t*>(&a), *reinterpret_cast<const uint32_t*>(&b)};
}
__device__ __forceinline__ uint32_t packz(cplx z) { return pack2h(z.r, z.i); }
__device__ __forceinline__ void wgmma_kg(float (&d)[24], uint64_t da, uint64_t db, int scale_d) {
    asm volatile("{\n.reg .pred p;\nsetp.ne.b32 p, %26, 0;\n"
                 "wgmma.mma_async.sync.aligned.m64n48k16.f32.f16.f16 "
                 "{%0,%1,%2,%3,%4,%5,%6,%7,%8,%9,%10,%11,%12,%13,%14,%15,%16,%17,%18,%19,%20,%21,%22,%23}, %24, %25, p, 1, 1, 1, 1;\n}\n"
                 : "+f"(d[0]), "+f"(d[1]), "+f"(d[2]), "+f"(d[3]), "+f"(d[4]), "+f"(d[5]), "+f"(d[6]), "+f"(d[7]), "+f"(d[8]), "+f"(d[9]),
                   "+f"(d[10]), "+f"(d[11]), "+f"(d[12]), "+f"(d[13]), "+f"(d[14]), "+f"(d[15]), "+f"(d[16]), "+f"(d[17]), "+f"(d[18]), "+f"(d[19]),
                   "+f"(d[20]), "+f"(d[21]), "+f"(d[22]), "+f"(d[23])
                 : "l"(da), "l"(db), "r"(scale_d));
}

struct SsmParams { const bf16 *lar, *aim, *cre, *cim, *logdt, *dskip; };
constexpr int KG_TABLES = 6 * 16384, KG_RES = 3136, KG_IDX = 6 * KG_RES, KG_DUMP = KG_IDX + 4096;
struct KgShared { uint32_t kmax[6]; };
struct KgParams { uint32_t l[3], a[3], r[3], i[3], dt, ds; };

__device__ __forceinline__ void kgen_load(KgParams& kp, int d0, int warp, int lane, const SsmParams& sp) {
    const int d = d0 + (warp < 8 ? 2 * (warp >> 2) + (warp & 1) : 4), idx = d * (NMODE / 2) + lane;
    const bf16 *pr = (warp & 2) ? sp.cre : sp.lar, *pi = (warp & 2) ? sp.cim : sp.aim;
#pragma unroll
    for (int j = 0; j < 3; j++) {
        kp.l[j] = __ldg((const uint32_t*)sp.lar + idx + 32 * j); kp.a[j] = __ldg((const uint32_t*)sp.aim + idx + 32 * j);
        kp.r[j] = __ldg((const uint32_t*)pr + idx + 32 * j); kp.i[j] = __ldg((const uint32_t*)pi + idx + 32 * j);
    }
    kp.dt = __ldg((const uint16_t*)sp.logdt + d);
    kp.ds = __ldg((const uint16_t*)sp.dskip + d0 + min(warp >> 1, 4));
}

struct KgAnchors { uint32_t v[8]; };
__device__ __forceinline__ KgAnchors kg_anchor_lo(const KgParams& kp, uint32_t sel, float dt) {
    auto B = [&](uint32_t v) { return __uint_as_float(__byte_perm(v, 0u, sel)); };
    const float arl = -rbf(ex2(B(kp.l[0]) * 1.4426950408889634f)) * dt * 1.4426950408889634f, ai = B(kp.a[0]) * dt;
    const cplx z8 = cexp_p(arl, ai, 8.f), z16 = csq(z8), z24 = cmul(z16, z8), z32 = csq(z16), z64 = csq(z32), z128 = csq(z64), z192 = cmul(z128, z64);
    return {{pack2h(1.f, z8.r), pack2h(0.f, z8.i), pack2h(z16.r, z24.r), pack2h(z16.i, z24.i), packz(z32), packz(z64), packz(z128), packz(z192)}};
}
__device__ __forceinline__ KgAnchors kg_anchor_hi(const KgParams& kp, uint32_t sel, float dt, float cs) {
    auto B = [&](uint32_t v) { return __uint_as_float(__byte_perm(v, 0u, sel)); };
    const float arl = -rbf(ex2(B(kp.l[0]) * 1.4426950408889634f)) * dt * 1.4426950408889634f, ai = B(kp.a[0]) * dt;
    const cplx z1 = cexp_p(arl, -ai, 1.f), z2 = csq(z1), z4 = csq(z2), z256 = cexp_p(arl, -ai, 256.f), z512 = csq(z256), z1024 = csq(z512);
    const cplx H0 = {B(kp.r[0]) * cs, -B(kp.i[0]) * cs}, H4 = cmul(H0, z4);
    return {{pack2h(H0.r, H4.r), pack2h(H0.i, H4.i), packz(z1), packz(z2), packz(z256), packz(z512), packz(z1024), 0u}};
}

template <class Hook>
__device__ __forceinline__ void kgen_tables(KgParams& kp, uint32_t scr, uint32_t dump, KgShared* ks, int warp, int lane, Hook hook TS_ARG) {
    const int wg = warp >> 2, half = warp & 1, sw = lane & 7;
    const bool hi = warp & 2;
    TS(23);
    const float dt = rbf(ex2(bf_lo(kp.dt) * 1.4426950408889634f));
    uint32_t sel = (wg == 2 && half) ? 0x3244u : 0x1044u;
    float cs = 0.f;
    KgAnchors an;
    if (hi) {
        uint32_t m = 0;
#pragma unroll
        for (int j = 0; j < 3; j++) m = __vmaxu2(m, __vmaxu2(kp.r[j] & 0x7FFF7FFFu, kp.i[j] & 0x7FFF7FFFu));
        m = __reduce_max_sync(~0u, max(m << 16, m & 0xFFFF0000u));
        const uint32_t e = min(max(__float_as_uint(2.f * dt * __uint_as_float(m)) >> 23, 2u), 252u);
        cs = 2.f * dt * __uint_as_float((253u - e) << 23);
        if (lane == 0) sts32(dump + (2 * wg + half) * KG_RES, (e + 1u) << 23);
        an = kg_anchor_hi(kp, sel, dt, cs);
    } else {
        an = kg_anchor_lo(kp, sel, dt);
    }
    if (an.v[0] != 0xFFFFFFFFu) hook();
    float acc[24];
    const int nstep = wg == 2 ? 3 : 6;
#pragma unroll 1
    for (int c = 0; c < nstep; c++) {
        if (wg < 2) sel ^= 0x2200u;
        if (wg == 2 || (c & 1)) {
#pragma unroll
            for (int j = 0; j < 2; j++) { kp.l[j] = kp.l[j + 1]; kp.a[j] = kp.a[j + 1]; kp.r[j] = kp.r[j + 1]; kp.i[j] = kp.i[j + 1]; }
        }
        const uint32_t buf = scr + (2 * wg + (c & 1)) * 16384, tb = buf + lane * 128;
        if (!hi) {
            cpair p[4];
            p[0] = {an.v[0], an.v[1]}; p[1] = {an.v[2], an.v[3]};
            p[2] = pmul(p[0], an.v[4]); p[3] = pmul(p[1], an.v[4]);
#pragma unroll
            for (int j = 0; j < 4; j++) {
                cpair v[4];
#pragma unroll
                for (int i = 0; i < 4; i++) v[i] = j ? pmul(p[i], an.v[4 + j]) : p[i];
                const uint32_t a = tb + (((4 * half + j) ^ sw) << 4);
                sts128(a, make_uint4(v[0].r, v[1].r, v[2].r, v[3].r));
                sts128(a + 4096, make_uint4(v[0].i, v[1].i, v[2].i, v[3].i));
            }
            an = kg_anchor_lo(kp, sel, dt);
        } else {
            const uint32_t h1 = an.v[2], h2 = an.v[3], h256 = an.v[4], h512 = an.v[5], h1024 = an.v[6];
            cpair p[11];
            p[0] = {an.v[0], an.v[1]};
            p[1] = pmul(p[0], h2); p[2] = pmul(p[0], h1); p[3] = pmul(p[1], h1);
            p[4] = pmul(p[0], h256); p[5] = pmul(p[1], h256); p[6] = pmul(p[0], h512); p[7] = pmul(p[4], h512);
            p[8] = pmul({__byte_perm(p[0].r, p[4].r, 0x5410), __byte_perm(p[0].i, p[4].i, 0x5410)}, h1024);
            p[9] = pmul(p[8], h512); p[10] = pmul(p[8], h1024);
#pragma unroll
            for (int j = 0; j < 3; j++) {
                const uint32_t a = tb + 8192 + (((3 * half + j) ^ sw) << 4);
                sts128(a, make_uint4(p[4 * j].r, p[4 * j + 1].r, p[4 * j + 2].r, p[j < 2 ? 4 * j + 3 : 10].r));
                sts128(a + 4096, make_uint4(p[4 * j].i, p[4 * j + 1].i, p[4 * j + 2].i, p[j < 2 ? 4 * j + 3 : 10].i));
            }
            an = kg_anchor_hi(kp, sel, dt, cs);
        }
        if (c == 0) TS(24);
        if (c == 2) TS(26);
        fence_async_smem();
        wg_wait<0>();
        named_bar(5 + wg, 128);
        if (c == 1) TS(25);
        if (c == 2) TS(28);
        const uint64_t da = mkdesc(buf, 4096, 1024, 1);
        wg_fence();
#pragma unroll
        for (int k = 0; k < 4; k++) wgmma_kg(acc, da + k * 128, da + 512 + k * 128, k > 0 || c > 0);
        wg_commit();
    }
    const int lo0 = 16 * half + (lane >> 2);
    const uint32_t ob = dump + (2 * wg + (hi ? 1 : 0)) * KG_RES, o = ob + (lo0 * 24 + 2 * (lo0 >> 2) + 2 * (lane & 3)) * 4;
    const float ci = __uint_as_float(lds32(ob));
    const float ds = (lane == 0 && warp <= 8 && !half) ? bf_lo(kp.ds) : 0.f;
    named_bar(5 + wg, 128);
    wg_wait<0>();
    float m = 0.f;
#pragma unroll
    for (int j = 0; j < 3; j++)
#pragma unroll
        for (int h = 0; h < 2; h++) {
            const float v0 = fmaf(ci, hi ? acc[12 + 4 * j + 2 * h] : acc[4 * j + 2 * h], j + h ? 0.f : ds), v1 = ci * (hi ? acc[13 + 4 * j + 2 * h] : acc[4 * j + 2 * h + 1]);
            asm volatile("st.shared.v2.f32 [%0], {%1, %2};" ::"r"(o + h * 784 + j * 32), "f"(v0), "f"(v1) : "memory");
            m = fmaxf(m, fmaxf(fabsf(v0), fabsf(v1)));
        }
    const uint32_t mm = __reduce_max_sync(~0u, __float_as_uint(m));
    if (lane == 0) asm volatile("red.shared.max.u32 [%0], %1;" ::"r"(s2u(&ks->kmax[2 * wg + (hi ? 1 : 0)])), "r"(mm) : "memory");
}

__device__ __forceinline__ void kgen_expand(int d0, uint32_t dump, KgShared* ks, int ht TS_ARG) {
    const int lane = ht & 31;
    auto F = [](uint32_t x) { return __uint_as_float(x); };
#pragma unroll 1
    for (int task = ht >> 5; task < 20; task += 3) {
        const int c = task >> 2, it = (task & 3) * 32 + lane, a = it >> 2, d = d0 + c;
        const uint4 o0 = lds128(dump + KG_IDX + it * 16), o1 = lds128(dump + KG_IDX + 2048 + it * 16);
        const uint32_t e = min(max(__float_as_uint(F(ks->kmax[c]) + (c == 4 ? F(ks->kmax[5]) : 0.f)) >> 23, 4u), 250u), b = dump + c * KG_RES;
        const float sc = __uint_as_float((253u - e) << 23);
        if (it == 0) g_ksc[d] = e;
        float x[16];
#pragma unroll
        for (int i = 0; i < 8; i++) {
            const uint32_t w = u4(i < 4 ? o0 : o1, i & 3);
            x[2 * i] = F(lds32(b + (w & 0xFFFF))); x[2 * i + 1] = F(lds32(b + (w >> 16)));
        }
        if (c == 4) {
#pragma unroll
            for (int i = 0; i < 8; i++) {
                const uint32_t w = u4(i < 4 ? o0 : o1, i & 3);
                x[2 * i] += F(lds32(b + KG_RES + (w & 0xFFFF))); x[2 * i + 1] += F(lds32(b + KG_RES + (w >> 16)));
            }
        }
        uint32_t ev[4], ov[4];
#pragma unroll
        for (int i = 0; i < 4; i++) {
            ev[i] = pack2h((x[2 * i] + x[8 + 2 * i]) * sc, (x[2 * i + 1] + x[9 + 2 * i]) * sc);
            ov[i] = pack2h((x[2 * i] - x[8 + 2 * i]) * sc, (x[2 * i + 1] - x[9 + 2 * i]) * sc);
        }
        uint32_t* dst = &g_keo[d >> 1][a * 32 + (((4 * (d & 1) + (it & 3)) ^ (a & 7)) << 2)];
        stg128(dst, make_uint4(ev[0], ev[1], ev[2], ev[3]));
        stg128(dst + 1024, make_uint4(ov[0], ov[1], ov[2], ov[3]));
    }
}
__device__ __forceinline__ void wgmma_h64_rs(uint32_t (&d)[16], const uint4& a, uint64_t db, int scale_d) {
    asm volatile("{\n.reg .pred p;\nsetp.ne.b32 p, %21, 0;\n"
                 "wgmma.mma_async.sync.aligned.m64n64k16.f16.f16.f16 {%0,%1,%2,%3,%4,%5,%6,%7,%8,%9,%10,%11,%12,%13,%14,%15}, {%16,%17,%18,%19}, %20, p, 1, 1, 1;\n}\n"
                 : "+r"(d[0]), "+r"(d[1]), "+r"(d[2]), "+r"(d[3]), "+r"(d[4]), "+r"(d[5]), "+r"(d[6]), "+r"(d[7]), "+r"(d[8]), "+r"(d[9]),
                   "+r"(d[10]), "+r"(d[11]), "+r"(d[12]), "+r"(d[13]), "+r"(d[14]), "+r"(d[15])
                 : "r"(a.x), "r"(a.y), "r"(a.z), "r"(a.w), "l"(db), "r"(scale_d));
}
__device__ __forceinline__ void wgmma_h32_rs(uint32_t (&d)[8], const uint32_t (&a)[4], uint64_t db, int scale_d) {
    asm volatile("{\n.reg .pred p;\nsetp.ne.b32 p, %13, 0;\n"
                 "wgmma.mma_async.sync.aligned.m64n32k16.f16.f16.f16 {%0,%1,%2,%3,%4,%5,%6,%7}, {%8,%9,%10,%11}, %12, p, 1, 1, 0;\n}\n"
                 : "+r"(d[0]), "+r"(d[1]), "+r"(d[2]), "+r"(d[3]), "+r"(d[4]), "+r"(d[5]), "+r"(d[6]), "+r"(d[7])
                 : "r"(a[0]), "r"(a[1]), "r"(a[2]), "r"(a[3]), "l"(db), "r"(scale_d));
}
__device__ __forceinline__ void wgmma_sp64_rs(float (&d)[32], const uint4& a, uint64_t db, uint32_t meta, int scale_d) {
    asm volatile("{\n.reg .pred p;\nsetp.ne.b32 p, %38, 0;\n"
                 "wgmma.mma_async.sp.sync.aligned.m64n64k32.f32.f16.f16 "
                 "{%0,%1,%2,%3,%4,%5,%6,%7,%8,%9,%10,%11,%12,%13,%14,%15,%16,%17,%18,%19,%20,%21,%22,%23,%24,%25,%26,%27,%28,%29,%30,%31}, "
                 "{%32,%33,%34,%35}, %36, %37, 0, p, 1, 1, 1;\n}\n"
                 : "+f"(d[0]), "+f"(d[1]), "+f"(d[2]), "+f"(d[3]), "+f"(d[4]), "+f"(d[5]), "+f"(d[6]), "+f"(d[7]), "+f"(d[8]), "+f"(d[9]),
                   "+f"(d[10]), "+f"(d[11]), "+f"(d[12]), "+f"(d[13]), "+f"(d[14]), "+f"(d[15]), "+f"(d[16]), "+f"(d[17]), "+f"(d[18]), "+f"(d[19]),
                   "+f"(d[20]), "+f"(d[21]), "+f"(d[22]), "+f"(d[23]), "+f"(d[24]), "+f"(d[25]), "+f"(d[26]), "+f"(d[27]), "+f"(d[28]), "+f"(d[29]),
                   "+f"(d[30]), "+f"(d[31])
                 : "r"(a.x), "r"(a.y), "r"(a.z), "r"(a.w), "l"(db), "r"(meta), "r"(scale_d));
}

__device__ __forceinline__ void fft_stage(const uint32_t (&u)[2][2][4], uint32_t eo, int warp4, int lane) {
    const int mi = lane >> 3, mj = lane & 7;
#pragma unroll
    for (int c = 0; c < 2; c++) {
        const uint32_t a = eo + (8 * warp4 + mj) * 128 + (((4 * c + mi) ^ mj) << 4);
        stsm_x4(a, hadd(u[c][0][0], u[c][1][0]), hadd(u[c][0][1], u[c][1][1]), hadd(u[c][0][2], u[c][1][2]), hadd(u[c][0][3], u[c][1][3]));
        stsm_x4(a + 4096, hsub(u[c][0][0], u[c][1][0]), hsub(u[c][0][1], u[c][1][1]), hsub(u[c][0][2], u[c][1][2]), hsub(u[c][0][3], u[c][1][3]));
    }
    fence_async_smem();
}
template <class Mid>
__device__ __forceinline__ void fft_forward(const uint4 (&a1)[4], const uint4 (&tw)[4], uint32_t eo, uint32_t s2, uint32_t (&X)[2][2][8], Mid mid) {
    uint32_t dr[16], di[16];
    const uint64_t de = mkdesc(eo, 4096, 1024, 1), d2 = mkdesc(s2, 16, 1024, 1);
    wg_fence();
    wgmma_h64_rs(dr, a1[0], de, 0);
    wgmma_h64_rs(di, a1[2], de + 256, 0);
    wgmma_h64_rs(dr, a1[1], de + 128, 1);
    wgmma_h64_rs(di, a1[3], de + 384, 1);
    wg_commit();
    mid();
    wg_wait<0>();
#pragma unroll
    for (int c = 0; c < 2; c++) {
        uint32_t zr[2][4], zi[2][4];
#pragma unroll
        for (int p = 0; p < 2; p++)
#pragma unroll
            for (int i = 0; i < 4; i++) {
                const uint32_t r = dr[8 * c + 4 * p + i], m = di[8 * c + 4 * p + i], tr = u4(tw[p], i), ti = u4(tw[2 + p], i);
                zr[p][i] = hfms(m, ti, hmul(r, tr));
                zi[p][i] = hfma(m, tr, hmul(r, ti));
            }
        wg_fence();
        wgmma_h32_rs(X[c][0], zr[0], d2, 0);
        wgmma_h32_rs(X[c][1], zr[1], d2 + 4, 0);
        wgmma_h32_rs(X[c][0], zi[0], d2 + 2, 1);
        wgmma_h32_rs(X[c][1], zi[1], d2 + 6, 1);
        wg_commit();
    }
}

template <class Mid, class Ready>
__device__ __forceinline__ void conv_pair(int ch0, int layer, uint32_t eo, uint32_t zb, uint32_t s23, uint32_t kbar, int warp, int lane,
                                          uint4 (&a1)[4], uint4 (&tw)[4], Mid mid, Ready ready TS_ARG) {
    const int wg = warp >> 2, w = warp & 3, t = 32 * w + lane, g = lane >> 2, q = lane & 3, mi = lane >> 3, mj = lane & 7;
    const bf16* xT = g_x1T;
    const float* sums = g_sums[layer][0];
    uint32_t u[2][2][4], KH[2][2][8];
    TS(1);
    mbar_wait(kbar, 0);
    TS(2);
    fft_forward(a1, tw, eo, s23, KH, mid);
    const uint2 ke = ldg64(g_ksc + ch0);
    named_bar(1 + wg, 128);
#pragma unroll
    for (int i = 0; i < 4; i++) tw[i] = ldg_tab(4 + i, t);
    const uint32_t oscale[2] = {(ke.x + 3u) * 0x00800080u, (ke.y + 3u) * 0x00800080u};
    wg_wait<0>();
    TS(4);
    ready();
    TS(5);
    uint2 x[2][2][2];
    const int ra[2] = {16 * (8 * w + g) + 4 * q, 16 * (63 - 8 * w - g) + 4 * q};
    {
        uint4 s[2][2][2];
#pragma unroll
        for (int h = 0; h < 2; h++)
#pragma unroll
            for (int p = 0; p < 2; p++) {
                s[h][p][0] = ldg128(sums + 1024 * p + ra[h]);
                s[h][p][1] = ldg128(sums + SEQ + 1024 * p + ra[h]);
#pragma unroll
                for (int c = 0; c < 2; c++) x[c][h][p] = ldg64(xT + (size_t)(ch0 + c) * XP + 1024 * p + ra[h]);
            }
        TS(6);
#pragma unroll
        for (int h = 0; h < 2; h++)
#pragma unroll
            for (int j = 0; j < 4; j++) {
                const uint4 sa = s[h][j >> 1][0], sq = s[h][j >> 1][1];
                const float4 v = make_float4(__uint_as_float(u4(sa, 2 * (j & 1))), __uint_as_float(u4(sq, 2 * (j & 1))),
                                             __uint_as_float(u4(sa, 2 * (j & 1) + 1)), __uint_as_float(u4(sq, 2 * (j & 1) + 1)));
                const float m0 = v.x * (1.0f / DM), m1 = v.z * (1.0f / DM);
                const float r0 = frsq(fmaxf(fmaf(v.y, 1.0f / DM, fmaf(-m0, m0, 1e-5f)), 1e-5f));
                const float r1 = frsq(fmaxf(fmaf(v.w, 1.0f / DM, fmaf(-m1, m1, 1e-5f)), 1e-5f));
                const float c0 = -m0 * r0, c1 = -m1 * r1;
#pragma unroll
                for (int c = 0; c < 2; c++) {
                    const uint32_t xv = (j & 1) ? x[c][h][j >> 1].y : x[c][h][j >> 1].x;
                    u[c][h][j] = pack2h(fmaf(bf_lo(xv), r0, c0), fmaf(bf_hi(xv), r1, c1));
                }
            }
    }
    TS(8);
    uint32_t X[2][2][8], Y[2][2][8];
    fft_stage(u, eo, w, lane);
    TS(9);
    named_bar(1 + wg, 128);
    fft_forward(a1, tw, eo, s23, X, [] {});
    TS(10);
#pragma unroll
    for (int i = 0; i < 4; i++) a1[i] = ldg_tab(12 + i, t);
    const uint64_t d3 = mkdesc(s23 + 4096, 16, 1024, 1);
#pragma unroll
    for (int c = 0; c < 2; c++) {
        wg_wait<1>();
        TS(11 + c);
        uint32_t pr[2][4], pi[2][4];
#pragma unroll
        for (int i = 0; i < 4; i++) {
            const uint32_t er = X[c][0][i], ei = X[c][0][4 + i], orr = X[c][1][i], oi = X[c][1][4 + i];
            const uint32_t ar = KH[c][0][i], ai = KH[c][0][4 + i], br = KH[c][1][i], bi = KH[c][1][4 + i];
            pr[0][i] = hfms(bi, oi, hfma(br, orr, hfms(ai, ei, hmul(ar, er))));
            pi[0][i] = hfma(bi, orr, hfma(br, oi, hfma(ai, er, hmul(ar, ei))));
            pr[1][i] = hfms(ai, oi, hfma(ar, orr, hfms(bi, ei, hmul(br, er))));
            pi[1][i] = hfma(ai, orr, hfma(ar, oi, hfma(bi, er, hmul(br, ei))));
        }
        wg_fence();
        wgmma_h32_rs(Y[c][0], pr[0], d3, 0);
        wgmma_h32_rs(Y[c][1], pr[1], d3 + 4, 0);
        wgmma_h32_rs(Y[c][0], pi[0], d3 + 2, 1);
        wgmma_h32_rs(Y[c][1], pi[1], d3 + 6, 1);
        wg_commit();
    }
#pragma unroll
    for (int c = 0; c < 2; c++) {
        if (c == 0) wg_wait<1>(); else wg_wait<0>();
        TS(13 + c);
        uint32_t zr[2][4], zi[2][4];
#pragma unroll
        for (int p = 0; p < 2; p++)
#pragma unroll
            for (int i = 0; i < 4; i++) {
                const uint32_t r = Y[c][p][i], m = Y[c][p][4 + i], tr = u4(tw[p], i), ti = u4(tw[2 + p], i);
                zr[i & 1][2 * p + (i >> 1)] = hfma(m, ti, hmul(r, tr));
                zi[i & 1][2 * p + (i >> 1)] = hfms(r, ti, hmul(m, tr));
            }
        const int kr = 4 * (mj >> 1) + (mj & 1) + 2 * (mj >> 2), ki = kr ^ 2;
#pragma unroll
        for (int h = 0; h < 2; h++) {
            const uint32_t a = zb + (2 * w + h) * 2048;
            stsm_x4(a + kr * 128 + (((4 * c + mi) ^ (kr & 7)) << 4), zr[h][0], zr[h][1], zr[h][2], zr[h][3]);
            stsm_x4(a + ki * 128 + (((4 * c + mi) ^ (ki & 7)) << 4), zi[h][0], zi[h][1], zi[h][2], zi[h][3]);
        }
    }
    TS(15);
    fence_async_smem();
    TS(16);
    named_bar(1 + wg, 128);
    TS(17);
    float acc[32];
    const uint64_t dz = mkdesc(zb, 4096, 1024, 1);
    wg_fence();
#pragma unroll
    for (int ks = 0; ks < 4; ks++) wgmma_sp64_rs(acc, a1[ks], dz + ks * 256, 0x44EEEE44u, ks > 0);
    wg_commit();
    wg_wait<0>();
    TS(18);
#pragma unroll
    for (int p = 0; p < 2; p++) {
        uint32_t r[2][2][2];
#pragma unroll
        for (int c = 0; c < 2; c++)
#pragma unroll
            for (int j = 0; j < 2; j++) {
                const float* d = acc + 4 * (4 * c + 2 * p + j);
                const uint32_t y0 = pack2(d[0] + d[2], d[1] + d[3]), y1 = pack2(d[0] - d[2], d[1] - d[3]);
                asm("fma.rn.bf16x2 %0, %1, %2, %3;" : "=r"(r[c][0][j]) : "r"(y0), "r"(oscale[c]), "r"(j ? x[c][0][p].y : x[c][0][p].x));
                asm("fma.rn.bf16x2 %0, %1, %2, %3;" : "=r"(r[c][1][j]) : "r"(y1), "r"(oscale[c]), "r"(j ? x[c][1][p].y : x[c][1][p].x));
            }
#pragma unroll
        for (int h = 0; h < 2; h++) {
            if (layer == 0) {
#pragma unroll
                for (int c = 0; c < 2; c++) *(uint2*)(g_x2T + (size_t)(ch0 + c) * XP + 1024 * p + ra[h]) = make_uint2(r[c][h][0], r[c][h][1]);
            } else {
                const uint32_t v0 = __byte_perm(r[0][h][0], r[1][h][0], 0x5410);
                st_ll4((uint4*)&g_fin[ch0 >> 1][1024 * p + ra[h]], v0 ? v0 : 0x80000000u, __byte_perm(r[0][h][0], r[1][h][0], 0x7632),
                       __byte_perm(r[0][h][1], r[1][h][1], 0x5410), __byte_perm(r[0][h][1], r[1][h][1], 0x7632));
            }
        }
    }
    TS(19);
}

#define Q_SCHED 0
#define Q_WAITFOR(it) (Q_SCHED == 0 ? (it) - 2 : Q_SCHED == 1 ? ((it) == 3 ? 1 : 0) : Q_SCHED == 2 ? -1 : (it) - 1)
#define Q_S0 8
#define Q_WGATE 0
#define Q_ROT 0
#define O_ROT 0
#define K_EARLY 0
#define O_KAT 3
#define O_MASK 127u
#define O_DEPTH 3
#define O_GATE 0
#define FIN_SLEEP 100
#define F_WDELAY 1200
constexpr int Q_ST = 4;
constexpr int Q_AB = 16384, Q_BB = 30720, Q_SB = Q_AB + Q_BB;
constexpr int Q_EROW = 336;
constexpr int Q_ESLOT = 8 * Q_EROW;
constexpr int Q_EOFF = Q_ST * Q_SB;
constexpr int Q_KG = 2 * Q_SB;
constexpr int Q_KDUMP = Q_EOFF + 16384;
static_assert(6 * Q_ESLOT <= 16384, "exchange slots");
static_assert(Q_KG + KG_TABLES <= Q_KDUMP, "kernel generation layout");
constexpr int Q_SMEM = Q_KDUMP + KG_DUMP;
constexpr int F_EO = Q_EOFF, F_S23 = F_EO + 3 * 8192;
static_assert(F_S23 + 8192 <= Q_SMEM, "convolution layout");
__host__ __device__ constexpr int w_grp(int j) { return j < 7 ? 2 * Q_SB + j * 12800 : 20480; }
constexpr int W_RES = 0, W_OUT = Q_SB;

constexpr int Q_ZERO = Q_EOFF + 4096, Q_WOT = Q_EOFF + 8320;

__device__ unsigned g_epoch;
__device__ __align__(1024) unsigned g_bar[4][16][32];
__device__ __align__(1024) uint4 g_wop[8][80][10][8];
__device__ __align__(1024) uint4 g_csp[8][16][96];
__device__ __align__(1024) uint4 g_stp[16][8][64];
__device__ __align__(1024) uint4 g_halo[128][2][5][32];
__device__ __align__(1024) uint4 g_of[8][16][8][5][32];

struct Bars { uint64_t full[Q_ST], empty[Q_ST], wfull[3], ex[7], res, go, qdone, att, prep, kf, ardy, hdone, fdone, idx, kdone, att1; };
constexpr int NBAR = sizeof(Bars) / 8;
__device__ __forceinline__ void grid_wait(const unsigned* c, int n, unsigned target, int lane) {
    const unsigned* p = c + 32 * min(lane, n - 1);
    unsigned v;
    int spin = 0;
    do { asm volatile("ld.relaxed.gpu.global.u32 %0, [%1];" : "=r"(v) : "l"(p) : "memory"); } while (!__all_sync(~0u, (int)(v - target) >= 0) && ++spin < (1 << 18));
    fence_acquire();
}
__device__ __forceinline__ void grid_arrive(unsigned* c) {
    fence_release();
    asm volatile("red.relaxed.gpu.global.add.u32 [%0], 1;" ::"l"(c) : "memory");
}

#define TMAP(n) ([] { const CUtensorMap* p_; asm volatile("{\n.reg .b64 t;\nmov.b64 t, fused_kernel_param_" #n ";\ncvta.param.u64 %0, t;\n}" : "=l"(p_)); return p_; }())
extern "C" __global__ void __launch_bounds__(384, 1)
fused_kernel(const __grid_constant__ CUtensorMap mX0, const __grid_constant__ CUtensorMap mX1, const __grid_constant__ CUtensorMap mW,
             const __grid_constant__ CUtensorMap mWr,
             const __grid_constant__ CUtensorMap mRes0, const __grid_constant__ CUtensorMap mRes1, const __grid_constant__ CUtensorMap mOut,
             const __grid_constant__ CUtensorMap mWo, bf16* __restrict__ out, const SsmParams sp) {
    extern __shared__ __align__(1024) char smraw[];
    __shared__ __align__(8) Bars s_bar[2];
    __shared__ __align__(16) float s_cs[240], s_mean[2][64], s_rstd[2][72];
    __shared__ KgShared s_kg;
    __shared__ uint32_t s_epoch;
    const uint32_t sb = s2u(smraw);
    int tid, warp, lane, bx, rank, blk, hg, npair, pair0, rot, c0;
    auto indices = [&] {
        asm volatile("mov.u32 %0, %%tid.x;" : "=r"(tid));
        asm volatile("mov.u32 %0, %%ctaid.x;" : "=r"(bx));
        warp = __shfl_sync(~0u, tid >> 5, 0); lane = tid & 31;
        rank = bx & 1; blk = bx & 15; hg = bx >> 4;
        npair = 3 - rank; pair0 = 5 * (bx >> 1) + 3 * rank;
        const int u = ((blk >> 1) + hg) & 7;
        rot = (5 * u) >> 2; c0 = 16 * (u & 3);
    };
    indices();
    TS_DECL;
    TS_BEGIN;
    KgParams kp;
    kgen_load(kp, bx * 5, warp, lane, sp);
    const uint32_t epoch0 = ldg32(&g_epoch);
#define EPOCH lds32(s2u(&s_epoch))
    if (tid < 64) g_sums[0][0][64 * bx + tid] = 0.f;
    if (tid >= 64) stg128(&g_halo[bx][0][0][0] + tid - 64, make_uint4(0, 0, 0, 0));
    if (tid < 6) s_kg.kmax[tid] = 0u;
    if (tid == 256) { prefetch_tmap(TMAP(2)); prefetch_tmap(TMAP(3)); prefetch_tmap(TMAP(0)); prefetch_tmap(TMAP(7)); }
    if (tid == 320) { prefetch_tmap(TMAP(4)); prefetch_tmap(TMAP(6)); prefetch_tmap(TMAP(1)); prefetch_tmap(TMAP(5)); }
    if (tid < 260) sts128(sb + Q_ZERO + tid * 16, make_uint4(0, 0, 0, 0));
    if (elect_one()) {
#define BAR_IS(f) (i == offsetof(Bars, f) / 8)
#pragma unroll 1
        for (int i = warp; i < NBAR; i += 12) {
            const int cnt = (i >= 4 && i < 8) ? 16 : (BAR_IS(go) || BAR_IS(att1)) ? 4 : (BAR_IS(qdone) || BAR_IS(att)) ? 8 : BAR_IS(prep) ? 96 : BAR_IS(hdone) ? 6 : BAR_IS(fdone) ? npair : BAR_IS(kdone) ? 2 : 1;
            mbar_init(s2u(s_bar) + i * 8, cnt);
            mbar_init(s2u(s_bar) + (NBAR + i) * 8, cnt);
        }
        fence_mbar_init();
    }
    __syncwarp();
    TS(29);
    fence_async_smem();
    TS(30);
    __syncthreads();
    TS(31);
    cluster_arrive_relaxed();
    cluster_wait();
    TS(27);

    int layer = 0;
    uint32_t bars = s2u(s_bar);
#define BAR(f) (bars + (uint32_t)offsetof(Bars, f))
    auto chunk = [&](int it) { return Q_ROT ? it + rot - (it + rot >= 10 ? 10 : 0) : it < 2 ? rot + it : it - 2 < rot ? it - 2 : it; };
    auto osrc_of = [&](int j) { return O_ROT ? (hg + j) & 7 : j == 0 ? hg : j - 1 < hg ? j - 1 : j; };
    auto issue_w = [&](uint32_t bb, int it, int half) {
        const int s = it & (Q_ST - 1);
        const uint32_t fb = bb + 8 * s, db = sb + s * Q_SB + Q_AB + half * 15360;
        const int k0 = chunk(it) * 64 + half * 32;
#pragma unroll
        for (int p = 0; p < 3; p++) tma2d_mc(db + p * 4096, TMAP(2), p * DM + hg * 80, k0, fb, 3);
        tma3d_mc(db + 12288, TMAP(3), hg * 80 + 64, k0, 0, fb, 3);
    };
    auto issue_x = [&](int it) {
        const int s = it & (Q_ST - 1), kc = chunk(it);
        mbar_expect(BAR(full) + 8 * s, Q_SB);
        tma3d(sb + s * Q_SB, TMAP(0) + layer, (layer ? blk : kc) * 64, (layer ? kc : blk) * 64, 0, BAR(full) + 8 * s);
    };
    {
        if (warp == 8) {
            if (elect_one()) {
#pragma unroll 1
                for (int it = 0; it < 2; it++) { issue_w(BAR(full), it, rank); issue_x(it); }
                mbar_expect(BAR(idx), 4096 + 6400);
                bulk_g2s(sb + Q_KDUMP + KG_IDX, c_fft + 16 * 512, 4096, BAR(idx));
                asm volatile("cp.async.bulk.tensor.4d.shared::cluster.global.mbarrier::complete_tx::bytes [%0], [%1, {0, 0, %3, %4}], [%2];"
                             ::"r"(sb + Q_WOT), "l"(TMAP(7)), "r"(BAR(idx)), "r"(10 * hg), "r"(5 * blk) : "memory");
                prefetch_l2((const char*)c_fft + bx * (sizeof(c_fft) / 128), sizeof(c_fft) / 128);
            }
            __syncwarp();
        }
        kgen_tables(kp, sb + Q_KG, sb + Q_KDUMP, &s_kg, warp, lane, [&] {
            if (tid == 256) s_epoch = epoch0;
        } TS_PASS);
        if (warp <= 8) asm volatile("bar.arrive 8, 384;" ::: "memory");
        fence_async_smem();
        cluster_arrive_relaxed();
        TS(1);
    }

#pragma unroll 1
    for (; layer < 2; layer++, bars += sizeof(Bars)) {
    indices();
    TS_PHASE(2 * layer);
    uint4 fa1[4], ftw[4];
    auto conv_tables = [&] {
#pragma unroll
        for (int i = 0; i < 4; i++) { fa1[i] = ldg_tab(i, tid & 127); ftw[i] = ldg_tab(8 + i, tid & 127); }
    };
    if (warp >= 8) {
        asm volatile("setmaxnreg.dec.sync.aligned.u32 88;");
        if (warp == 8) {
            if (layer == 0) {
                cluster_wait();
            } else {
                grid_wait(g_bar[2][0], 10, 32 * (EPOCH + 1), lane);
                mbar_wait(BAR(fdone) - sizeof(Bars), 0);
                fence_async_global();
                TS(1);
            }
            if (elect_one()) {
#pragma unroll 1
                for (int it = layer ? 0 : 2; it < 10; it++) {
                    if (it >= Q_ST) mbar_wait(BAR(empty) + 8 * (it & (Q_ST - 1)), ((it >> 2) - 1) & 1);
                    else if (it > 0 && Q_WAITFOR(it) >= 0) mbar_wait(BAR(full) + 8 * Q_WAITFOR(it), 0);
                    if (it == Q_ST) mbar_wait(BAR(hdone), 0);
                    issue_x(it);
                    if (it >= Q_ST || layer == 0) issue_w(BAR(full), it, rank);
                }
                if (layer == 0) { mbar_wait(BAR(prep), 0); fence_async_global(); }
#pragma unroll 1
                for (int j = 0; j < 8; j++) {
                    const int b = (j + 1) >> 2;
                    const uint32_t fb = BAR(wfull) + 8 * b;
                    if (j == 0 || j == 3 || j == 7) {
                        mbar_wait(BAR(empty) + 8 * ((2 + b) & 3), b < 2);
                        TS(11 + b);
                        mbar_expect(fb, (b == 0 ? 3 : b == 1 ? 4 : 1) * 12800);
                    }
                    bulk_g2s_mc(sb + w_grp(j) + rank * 6400, &g_wop[hg][osrc_of(j) * 10 + rank * 5], 6400, fb, 3);
                }
                mbar_expect(BAR(res), 20480);
                if (layer == 0) tma3d(sb + W_RES, TMAP(0), hg * 80, blk * 64, 0, BAR(res));
                tma3d(sb + W_RES + (layer ? 0 : 16384), TMAP(4) + layer, layer ? blk * 64 : hg * 80 + 64, layer ? hg * 80 : blk * 64, 0, BAR(res));
                if (layer == 0) { mbar_wait(BAR(kdone), 0); fence_async_global(); }
                mbar_wait(BAR(att), 0);
                fence_async_smem();
                mbar_expect(BAR(kf), (npair + 1 - layer) * 8192);
                bulk_g2s(sb + F_EO, g_keo[pair0], npair * 8192, BAR(kf));
                if (layer == 0) bulk_g2s(sb + F_S23, c_fft + 18 * 512, 8192, BAR(kf));
            }
            __syncwarp();
        } else {
            const int ht = tid - 288, hw = warp - 9, mi = lane >> 3, mj = lane & 7, g = lane >> 2, q = lane & 3;
            auto F = [](uint32_t x) { return __uint_as_float(x); };
            auto U = [](float x) { return __float_as_uint(x); };
            const uint32_t lb = layer ^ 1, eb = ~EPOCH & 1u;
            if (layer == 0) {
                mbar_wait(BAR(idx), 0);
                if (hw == 2 && elect_one()) {
                    bulk_s2g(&g_wop[hg][5 * blk], sb + Q_WOT, 6400);
#pragma unroll 1
                    for (int i = 0; i < 5; i++) bulk_s2g((char*)g_fin + (bx * 5 + i) * (FP * 2), sb + Q_ZERO, FP * 2);
                    bulk_commit();
                }
                __syncwarp();
            }
            mbar_wait(BAR(full), 0);
            mbar_wait(BAR(full) + 8, 0);
            if (ht == 0) TSX(2, 2);
            if (layer == 0) {
                float cs[2][4] = {{0.f, 0.f, 0.f, 0.f}, {0.f, 0.f, 0.f, 0.f}};
#pragma unroll
                for (int G = 0; G < 5; G++) {
                    const int row = c0 + 40 * rank + 8 * G + mj;
                    const uint32_t b = sb + (row >> 6) * Q_SB + Q_AB + ((row >> 5) & 1) * 15360;
                    uint32_t r[10];
                    ldsm_x4_t(r[0], r[1], r[2], r[3], b + hw * 4096 + (row & 31) * 128 + ((mi ^ mj) << 4));
                    ldsm_x4_t(r[4], r[5], r[6], r[7], b + hw * 4096 + (row & 31) * 128 + (((4 + mi) ^ mj) << 4));
                    ldsm_x2_t(r[8], r[9], b + 12288 + hw * 1024 + (row & 31) * 32 + (((mi & 1) ^ (mj >> 2)) << 4));
#pragma unroll
                    for (int f = 0; f < 10; f += 2) {
                        const uint32_t a = g == (f & 7) ? 0x3F803F80u : 0u, c = g == (f & 7) + 1 ? 0x3F803F80u : 0u;
                        mma16816(cs[(f >> 1) & 1], f < 8 ? a : 0u, f < 8 ? 0u : a, f < 8 ? c : 0u, f < 8 ? 0u : c, r[f], r[f + 1]);
                    }
                }
                st_ll4(&g_csp[hg][blk][ht], (U(cs[0][0] + cs[1][0]) & ~1u) | eb, U(cs[0][1] + cs[1][1]), U(cs[0][2] + cs[1][2]), U(cs[0][3] + cs[1][3]));
            }
            uint32_t xf[3][20];
#pragma unroll
            for (int i = 0; i < 3; i++) {
                const int tile = min(hw + 3 * i, 7);
#pragma unroll
                for (int k = 0; k < 5; k++) {
                    const int ch = c0 + 16 * k + 8 * (mi >> 1), tok = 16 * (tile & 3) + 8 * (mi & 1);
                    const uint32_t a = sb + (ch >> 6) * Q_SB + (tile >> 2) * 8192;
                    if (layer == 0) ldsm_x4(xf[i][4 * k], xf[i][4 * k + 1], xf[i][4 * k + 2], xf[i][4 * k + 3], a + (tok + mj) * 128 + ((((ch & 63) >> 3) ^ mj) << 4));
                    else ldsm_x4_t(xf[i][4 * k], xf[i][4 * k + 1], xf[i][4 * k + 2], xf[i][4 * k + 3], a + ((ch & 63) + mj) * 128 + (((tok >> 3) ^ mj) << 4));
                }
            }
            fence_async_smem();
            __syncwarp();
            if (lane == 0) { mbar_arrive_cta(BAR(hdone), 0); mbar_arrive_cta(BAR(hdone), 1); }
            if (ht == 0) TSX(2, 3);
            if (layer == 0) {
                if (hw == 2 && elect_one()) { bulk_wait(); fence_async_global(); grid_arrive(g_bar[3][hg]); }
                __syncwarp();
                cluster_wait();
                named_bar(8, 384);
            }
            if (ht == 0) TSX(2, 8);
#pragma unroll
            for (int i = 0; i < 3; i++) {
                float a[4] = {0.f, 0.f, 0.f, 0.f};
#pragma unroll
                for (int j = 0; j < 20; j++) {
                    const float lo = bf_lo(xf[i][j]), hi = bf_hi(xf[i][j]);
                    a[2 * (j & 1)] += lo + hi; a[2 * (j & 1) + 1] = fmaf(lo, lo, fmaf(hi, hi, a[2 * (j & 1) + 1]));
                }
#pragma unroll
                for (int j = 0; j < 4; j++) { a[j] += __shfl_xor_sync(~0u, a[j], 1); a[j] += __shfl_xor_sync(~0u, a[j], 2); }
                if (q == 0 && hw + 3 * i < 8) st_ll4(&g_stp[blk][hg][8 * (hw + 3 * i) + g], (U(a[0]) & ~1u) | lb, U(a[1]), U(a[2]), U(a[3]));
            }
            if (ht == 0) TSX(2, 4);
            if (layer == 0) {
                float t[4] = {0.f, 0.f, 0.f, 0.f};
                uint4 v[16];
                int spin = 0;
                uint32_t bad;
                do {
                    bad = 0;
#pragma unroll
                    for (int j = 0; j < 16; j++) v[j] = ld_ll4(&g_csp[hg][j][ht]);
#pragma unroll
                    for (int j = 0; j < 16; j++) bad |= v[j].x ^ eb;
                } while ((bad & 1u) && ++spin < (1 << 18));
#pragma unroll
                for (int j = 0; j < 16; j++) { t[0] += F(v[j].x); t[1] += F(v[j].y); t[2] += F(v[j].z); t[3] += F(v[j].w); }
                *(float2*)&s_cs[80 * hw + 2 * lane] = make_float2(t[0], t[1]);
                if (lane < 8) *(float2*)&s_cs[80 * hw + 64 + 2 * lane] = make_float2(t[2], t[3]);
                if (hw == 2) grid_wait(g_bar[3][0], 8, 16 * (EPOCH + 1), lane);
            }
            if (ht == 0) TSX(2, 15);
            if (ht < 80) {
                const bool halo = ht >= 64;
                const int p = halo ? (ht >> 3) & 1 : ht >> 5, i = halo ? (ht & 7) - 8 : 8 + 2 * (ht & 24) + (ht & 7);
                const uint4* src = &g_stp[halo && blk ? blk - 1 : blk][0][halo ? 32 * p + 24 + (ht & 7) : ht];
                uint4 v[8];
                int spin = 0;
                uint32_t bad;
                do {
                    bad = 0;
#pragma unroll
                    for (int j = 0; j < 8; j++) v[j] = ld_ll4(src + 64 * j);
#pragma unroll
                    for (int j = 0; j < 8; j++) bad |= v[j].x ^ lb;
                } while ((bad & 1u) && ++spin < (1 << 18));
                float t[4] = {0.f, 0.f, 0.f, 0.f};
#pragma unroll
                for (int j = 0; j < 8; j++) { t[0] += F(v[j].x); t[1] += F(v[j].y); t[2] += F(v[j].z); t[3] += F(v[j].w); }
                const uint32_t s0 = ln_finish_packed(t[0], t[1]), s1 = ln_finish_packed(t[2], t[3]);
                if (!halo) { s_mean[p][i - 8] = bf_hi(s0); s_mean[p][i] = bf_hi(s1); s_rstd[p][i] = frcp(bf_lo(s0)); }
                s_rstd[p][i + 8] = frcp(bf_lo(s1));
            }
            fence_acquire();
            mbar_arrive(BAR(prep));
            if (ht == 0) TSX(2, 5);
            if (layer == 0) {
                __syncwarp();
                kgen_expand(bx * 5, sb + Q_KDUMP, &s_kg, ht TS_PASS);
                fence_async_smem();
                named_bar(4, 96);
                if (ht == 0) { fence_release(); mbar_arrive_cta(BAR(kdone), 0); mbar_arrive_cta(BAR(kdone), 1); }
                if (ht == 0) TSX(2, 7);
            }
        }
        __syncwarp();
        named_bar(3, 128);
        conv_tables();
        asm volatile("setmaxnreg.inc.sync.aligned.u32 168;");
    } else {
    const int wg = warp >> 2, w = warp & 3;
    const int mi = lane >> 3, mj = lane & 7, g = lane >> 2, q = lane & 3;
    TS(2);
    float acc[120];
#pragma unroll
    for (int i = 0; i < 120; i++) acc[i] = 0.f;
    auto release = [&](int it) {
        if (lane == 0) { mbar_arrive_cta(BAR(empty) + 8 * (it & (Q_ST - 1)), 0); mbar_arrive_cta(BAR(empty) + 8 * (it & (Q_ST - 1)), 1); }
    };
#pragma unroll 1
    for (int it = 0; it < 10; it++) {
        const int s = it & (Q_ST - 1);
        const uint32_t st = sb + s * Q_SB;
        const bool hold = wg == 1 && it == Q_S0;
        if (hold) {
            wg_wait<0>();
            release(it - 1);
            mbar_wait(BAR(go), 0);
        }
        mbar_wait(BAR(full) + 8 * (s), (it >> 2) & 1);
        if (it < 2) TS(3 + it);
        if (it == 6) TS(5);
        if (it == 9) TS(6);
        const uint64_t da = mkdesc(st + wg * 8192, 16, 1024, 1);
        const uint64_t db = mkdesc(st + Q_AB, 4096, 1024, 1);
        const uint64_t dr = mkdesc(st + Q_AB + 12288, 1024, 256, 3);
        if (layer == 0) {
            wg_fence();
#pragma unroll
            for (int ks = 0; ks < 4; ks++) {
                const int sc = 1;
                wgmma_n192<0, 1>(*(float(*)[96]) & acc[0], da + ks * 2, db + (ks >> 1) * 960 + (ks & 1) * 128, sc);
                wgmma_n48<0, 1>(*(float(*)[24]) & acc[96], da + ks * 2, dr + (ks >> 1) * 960 + (ks & 1) * 32, sc);
            }
            wg_commit();
        } else {
            wg_fence();
#pragma unroll
            for (int ks = 0; ks < 4; ks++) {
                const int sc = 1;
                wgmma_n192<1, 1>(*(float(*)[96]) & acc[0], da + ks * 128, db + (ks >> 1) * 960 + (ks & 1) * 128, sc);
                wgmma_n48<1, 1>(*(float(*)[24]) & acc[96], da + ks * 128, dr + (ks >> 1) * 960 + (ks & 1) * 32, sc);
            }
            wg_commit();
        }
        wg_wait<1>();
        if (it > 0 && !hold) release(it - 1);
    }
    if (wg == 0 && lane == 0) mbar_arrive(BAR(go));
    asm volatile("setmaxnreg.inc.sync.aligned.u32 208;");
    if (layer == 0) cluster_wait();
    mbar_wait(BAR(prep), 0);
    const uint32_t ob = layer ^ 1;
    const bool first = (blk == 0 && w == 0);
    const bool sel0 = (2 * q > g), sel1 = (2 * q + 1 > g);
    constexpr float SC = 0.22360679774997896f * 1.4426950408889634f;
    const float m0 = s_mean[wg][16 * w + g], m1 = s_mean[wg][8 + 16 * w + g];
    const float* rs = &s_rstd[wg][16 * w];
    const float kx0 = rs[2 * q + (sel0 ? 0 : 8)], kx1 = rs[2 * q + (sel1 ? 1 : 9)], ky0 = rs[2 * q + (sel0 ? 8 : 16)], ky1 = rs[2 * q + (sel1 ? 9 : 17)];
    const float cx0 = SC * rs[8 + g] * kx0, cx1 = SC * rs[8 + g] * kx1, cy0 = SC * rs[16 + g] * ky0, cy1 = SC * rs[16 + g] * ky1;
    wg_wait<0>();
    TS(7);
    if (lane == 0) mbar_arrive(BAR(qdone));
    uint32_t ql[10], qh[10], kl[10], kh[10], vl[10], vh[10];
    auto fold = [&](int p, int f, uint32_t& lo, uint32_t& hi) {
        const int j = (f < 8) ? 8 * p + f : 24 + 2 * p + (f - 8);
        const float2 c = *(const float2*)&s_cs[p * 80 + 8 * f + 2 * q];
        lo = pack2(fmaf(-m0, c.x, acc[4 * j]), fmaf(-m0, c.y, acc[4 * j + 1]));
        hi = pack2(fmaf(-m1, c.x, acc[4 * j + 2]), fmaf(-m1, c.y, acc[4 * j + 3]));
    };
#pragma unroll
    for (int f = 0; f < 10; f++) { fold(1, f, kl[f], kh[f]); fold(2, f, vl[f], vh[f]); }
    if (w == 3) {
        uint4* hp = &g_halo[bx][wg][0][lane];
#pragma unroll
        for (int f = 0; f < 5; f++) st_ll4(hp + 32 * f, (vh[2 * f] & ~1u) | ob, vh[2 * f + 1], kh[2 * f], kh[2 * f + 1]);
    } else {
        const uint32_t a = sb + Q_EOFF + (warp - wg) * Q_ESLOT + mj * Q_EROW + mi * 16;
        stsm_x4(a, kh[0], kh[1], kh[2], kh[3]);
        stsm_x4(a + 64, kh[4], kh[5], kh[6], kh[7]);
        stsm_x4(a + 128, kh[8], kh[9], vh[0], vh[1]);
        stsm_x4(a + 192, vh[2], vh[3], vh[4], vh[5]);
        stsm_x4(a + 256, vh[6], vh[7], vh[8], vh[9]);
        __syncwarp();
        if (lane == 0) mbar_arrive(BAR(ex) + 8 * (warp));
    }
    TS(9);
#pragma unroll
    for (int f = 0; f < 10; f++) fold(0, f, ql[f], qh[f]);
    uint32_t vt1[10], vt2[10];
#pragma unroll
    for (int f = 0; f < 10; f++) { vt1[f] = movm_t(vl[f]); vt2[f] = movm_t(vh[f]); }
    TS(10);
    uint32_t kp[10], vp[10];
    if (w > 0) {
        const uint32_t a = sb + Q_EOFF + (warp - wg - 1) * Q_ESLOT + mj * Q_EROW + mi * 16;
        mbar_wait(BAR(ex) + 8 * (warp - 1), 0);
        ldsm_x4(kp[0], kp[1], kp[2], kp[3], a);
        ldsm_x4(kp[4], kp[5], kp[6], kp[7], a + 64);
        ldsm_x2(kp[8], kp[9], a + 128);
        ldsm_x4_t(vp[0], vp[1], vp[2], vp[3], a + 160);
        ldsm_x4_t(vp[4], vp[5], vp[6], vp[7], a + 224);
        ldsm_x2_t(vp[8], vp[9], a + 288 - (lane >> 4) * 32);
    } else if (blk > 0) {
        const uint4* hp = &g_halo[bx - 1][wg][0][lane];
        uint4 hv[5];
        int spin = 0;
        uint32_t bad;
        do {
            bad = 0;
#pragma unroll
            for (int f = 0; f < 5; f++) hv[f] = ld_ll4(hp + 32 * f);
#pragma unroll
            for (int f = 0; f < 5; f++) bad |= hv[f].x ^ ob;
        } while (__any_sync(~0u, bad & 1u) && ++spin < (1 << 18));
#pragma unroll
        for (int f = 0; f < 10; f++) { kp[f] = u4(hv[f >> 1], 2 + (f & 1)); vp[f] = movm_t(u4(hv[f >> 1], f & 1)); }
    } else {
#pragma unroll
        for (int f = 0; f < 10; f++) { kp[f] = 0u; vp[f] = 0u; }
    }
    TS(12);
    float oacc[10][4];
#pragma unroll
    for (int h = 0; h < 4; h++) {
        const int fa = (h == 0) ? 0 : (h == 1) ? 3 : (h == 2) ? 5 : 8, fb = fa + 1, fh = (h < 2) ? 2 : 7;
        const bool mine = (h & 1) ? (q >= 2) : (q < 2);
        const uint32_t qml = mine ? ql[fh] : 0u, qmh = mine ? qh[fh] : 0u;
        float S0[4] = {0.f, 0.f, 0.f, 0.f}, S1[4] = {0.f, 0.f, 0.f, 0.f}, S2[4] = {0.f, 0.f, 0.f, 0.f};
        mma16816(S0, ql[fa], qh[fa], ql[fb], qh[fb], kp[fa], kp[fb]); mma1688(S0, qml, qmh, kp[fh]);
        mma16816(S1, ql[fa], qh[fa], ql[fb], qh[fb], kl[fa], kl[fb]); mma1688(S1, qml, qmh, kl[fh]);
        mma16816(S2, ql[fa], qh[fa], ql[fb], qh[fb], kh[fa], kh[fb]); mma1688(S2, qml, qmh, kh[fh]);
        float x0 = (sel0 ? S0[0] : S1[0]) * cx0, x1 = (sel1 ? S0[1] : S1[1]) * cx1;
        float y0 = (sel0 ? S1[2] : S2[2]) * cy0, y1 = (sel1 ? S1[3] : S2[3]) * cy1;
        if (first) { if (sel0) x0 = -INFINITY; if (sel1) x1 = -INFINITY; }
        float mx = fmaxf(x0, x1), my = fmaxf(y0, y1);
        mx = fmaxf(mx, __shfl_xor_sync(~0u, mx, 1)); my = fmaxf(my, __shfl_xor_sync(~0u, my, 1));
        mx = fmaxf(mx, __shfl_xor_sync(~0u, mx, 2)); my = fmaxf(my, __shfl_xor_sync(~0u, my, 2));
        x0 = ex2(x0 - mx); x1 = ex2(x1 - mx); y0 = ex2(y0 - my); y1 = ex2(y1 - my);
        float sx = x0 + x1, sy = y0 + y1;
        sx += __shfl_xor_sync(~0u, sx, 1); sy += __shfl_xor_sync(~0u, sy, 1);
        sx += __shfl_xor_sync(~0u, sx, 2); sy += __shfl_xor_sync(~0u, sy, 2);
        const float ix = frcp(sx), iy = frcp(sy);
        x0 *= ix * kx0; x1 *= ix * kx1; y0 *= iy * ky0; y1 *= iy * ky1;
        const uint32_t pa0 = pack2(sel0 ? x0 : 0.f, sel1 ? x1 : 0.f);
        const uint32_t pa2 = pack2(sel0 ? 0.f : x0, sel1 ? 0.f : x1);
        const uint32_t pa3 = pack2(sel0 ? y0 : 0.f, sel1 ? y1 : 0.f);
        const uint32_t pb1 = pack2(sel0 ? 0.f : y0, sel1 ? 0.f : y1);
#pragma unroll
        for (int i = 0; i < 3; i++) {
            const int f = (i == 0) ? fa : (i == 1) ? fb : fh;
            float O[4] = {0.f, 0.f, 0.f, 0.f};
            mma16816(O, pa0, 0u, pa2, pa3, vp[f], vt1[f]);
            mma1688(O, 0u, pb1, vt2[f]);
            if (i < 2 || !(h & 1) || mine) { oacc[f][0] = O[0]; oacc[f][1] = O[1]; oacc[f][2] = O[2]; oacc[f][3] = O[3]; }
        }
    }
    TS(13);
    uint4 of[7][5];
    {
        uint4* dst = &g_of[hg][blk][warp][0][lane];
#pragma unroll
        for (int k = 0; k < 5; k++) {
            of[0][k] = make_uint4(pack2(oacc[2 * k][0], oacc[2 * k][1]), pack2(oacc[2 * k][2], oacc[2 * k][3]),
                                  pack2(oacc[2 * k + 1][0], oacc[2 * k + 1][1]), pack2(oacc[2 * k + 1][2], oacc[2 * k + 1][3]));
            st_ll4(dst + 32 * k, (of[0][k].x & ~1u) | ob, of[0][k].y, of[0][k].z, of[0][k].w);
        }
    }
    if (Q_WGATE && wg == 1 && lane == 0) mbar_arrive(BAR(att1));
    TS(14);
    const uint4* osrc = &g_of[0][blk][warp][0][lane];
    auto oload = [&](int j) {
        const uint4* p = osrc + osrc_of(j) * 20480;
#pragma unroll
        for (int k = 0; k < 5; k++) of[j % 7][k] = ld_ll4(p + 32 * k);
    };
    float aw[40];
    auto omma = [&](int j) {
        const uint64_t dm = mkdesc(sb + w_grp(j), 1280, 128, 0);
        wg_fence();
#pragma unroll
        for (int k = 0; k < 5; k++) wgmma_rs80(aw, of[j % 7][k], dm + k * 160, j + k > 0);
        wg_commit();
    };
    if (Q_WGATE && wg == 0) mbar_wait(BAR(att1), 0);
    mbar_wait(BAR(wfull), 0);
    omma(0);
    TS(8);
    {
        const uint32_t* pp = &g_of[osrc_of(1 + min(lane, 6))][blk][warp][4][31].x;
        uint32_t v, m;
        int spin = 0;
        do {
            asm volatile("ld.relaxed.gpu.global.u32 %0, [%1];" : "=r"(v) : "l"(pp) : "memory");
            m = __ballot_sync(~0u, (v & 1u) != ob);
        } while ((m & O_MASK) && ++spin < (1 << 18));
        TS(15);
        if (O_GATE) named_bar(O_GATE == 1 ? 1 + wg : 9, O_GATE == 1 ? 128 : 256);
#pragma unroll
        for (int j = 1; j <= O_DEPTH; j++) oload(j);
        wg_wait<0>();
        TS(16);
    }
#pragma unroll
    for (int j = 1; j < 8; j++) {
        if (j == 3 || j == 7) mbar_wait(BAR(wfull) + 8 * ((j + 1) >> 2), 0);
        int spin = 0;
        while (true) {
            const uint4* f = of[j % 7];
            const uint32_t bad = ((f[0].x ^ ob) | (f[1].x ^ ob) | (f[2].x ^ ob) | (f[3].x ^ ob) | (f[4].x ^ ob)) & 1u;
            if (__all_sync(~0u, !bad) || ++spin >= (1 << 18)) break;
            oload(j);
        }
        if (j + O_DEPTH < 8) oload(j + O_DEPTH);
        if (j == 1) TS(17);
        if (j == 5) TS(18);
        omma(j);
        if (j == O_KAT && lane == 0) mbar_arrive(BAR(att));
    }
    wg_wait<2>();
    uint32_t res[20];
    mbar_wait(BAR(res), 0);
    const uint32_t ta = (8 * (mi >> 1) + mj) * 128 + (((2 * w + (mi & 1)) ^ mj) << 4);
    if (layer == 0) {
        const int tok = 16 * w + 8 * (mi & 1) + mj;
#pragma unroll
        for (int k = 0; k < 4; k++)
            ldsm_x4(res[4 * k], res[4 * k + 1], res[4 * k + 2], res[4 * k + 3], sb + W_RES + wg * 8192 + tok * 128 + (((2 * k + (mi >> 1)) ^ mj) << 4));
        ldsm_x4(res[16], res[17], res[18], res[19], sb + W_RES + 16384 + wg * 2048 + tok * 32 + (((mi >> 1) ^ (mj >> 2)) << 4));
    } else {
#pragma unroll
        for (int k = 0; k < 5; k++) ldsm_x4_t(res[4 * k], res[4 * k + 1], res[4 * k + 2], res[4 * k + 3], sb + W_RES + wg * 10240 + k * 2048 + ta);
    }
    mbar_wait(BAR(qdone), 0);
    wg_wait<0>();
    TS(19);
#pragma unroll
    for (int i = 0; i < 20; i++) {
        const uint32_t y = pack2(aw[2 * i], aw[2 * i + 1]);
        asm("add.rn.bf16x2 %0, %0, %1;" : "+r"(res[i]) : "r"(y));
    }
#pragma unroll
    for (int k = 0; k < 5; k++) stsm_x4_t(sb + W_OUT + wg * 10240 + k * 2048 + ta, res[4 * k], res[4 * k + 1], res[4 * k + 2], res[4 * k + 3]);
    fence_async_smem();
    named_bar(1 + wg, 128);
    if (w == 0 && elect_one()) {
        asm volatile("cp.async.bulk.tensor.2d.global.shared::cta.bulk_group [%0, {%2, %3}], [%1];"
                     ::"l"(TMAP(6)), "r"(sb + W_OUT + wg * 10240), "r"(1024 * wg + 64 * blk), "r"(hg * 80) : "memory");
        bulk_commit();
    }
    __syncwarp();
    conv_tables();
    TS(20);
    {
        float sm[4] = {0.f, 0.f, 0.f, 0.f}, d0[4] = {0.f, 0.f, 0.f, 0.f}, d1[4] = {0.f, 0.f, 0.f, 0.f};
#pragma unroll
        for (int k = 0; k < 5; k++) {
            mma16816(sm, res[4 * k], res[4 * k + 1], res[4 * k + 2], res[4 * k + 3], 0x3F803F80u, 0x3F803F80u);
            mma16816(d0, res[4 * k], res[4 * k + 1], res[4 * k + 2], res[4 * k + 3], res[4 * k], res[4 * k + 2]);
            mma16816(d1, res[4 * k], res[4 * k + 1], res[4 * k + 2], res[4 * k + 3], res[4 * k + 1], res[4 * k + 3]);
        }
        const bool diag = q == (g >> 1);
        if (diag || q == ((g >> 1) ^ 1)) {
            float* dst = g_sums[layer][diag] + 1024 * wg + 64 * blk + 16 * w + g;
            asm volatile("red.global.add.f32 [%0], %1;" ::"l"(dst), "f"(diag ? ((g & 1) ? d0[1] : d0[0]) : sm[0]) : "memory");
            asm volatile("red.global.add.f32 [%0], %1;" ::"l"(dst + 8), "f"(diag ? ((g & 1) ? d1[3] : d1[2]) : sm[2]) : "memory");
        }
    }
    TS(21);
    named_bar(1 + wg, 128);
    asm volatile("setmaxnreg.dec.sync.aligned.u32 168;");
    TS(22);
    }
    TS_PHASE(2 * layer + 1);
    TS(0);
    indices();
    const int wg = warp >> 2;
    if (wg < npair) {
        conv_pair(2 * (pair0 + wg), layer, sb + F_EO + wg * 8192, sb + wg * Q_SB, sb + F_S23, BAR(kf), warp, lane, fa1, ftw, [&] {
            if (wg < 2 && (warp & 3) == 0 && elect_one()) { bulk_wait(); fence_async_global(); grid_arrive(g_bar[layer][hg]); }
            __syncwarp();
        }, [&] {
            if (warp == 0) {
                grid_wait(g_bar[layer][0], 8, 32 * (EPOCH + 1), lane);
                if (lane == 0) mbar_arrive(BAR(ardy));
            } else {
                mbar_wait(BAR(ardy), 0);
            }
        } TS_PASS);
        if (layer == 0) {
            named_bar(1 + wg, 128);
            if ((tid & 127) == 0) { mbar_arrive(BAR(fdone)); grid_arrive(g_bar[2][(pair0 + wg) >> 5]); }
            __syncwarp();
        }
    } else if (layer == 0 && warp == 8) {
        mbar_wait(BAR(ardy), 0);
        const long long t0 = clock64();
        while (clock64() - t0 < F_WDELAY) {}
        if (elect_one()) {
#pragma unroll 1
            for (int i = 0; i < 2 * Q_ST; i++) issue_w(BAR(full) + sizeof(Bars), i >> 1, i & 1);
        }
        __syncwarp();
    }
    if (wg >= npair) named_bar(3, 128);
    TS(20);
    }
    indices();
    __syncthreads();
    if (tid < 320) {
        const int cq = (warp & ~1) + (lane & 1), tg = 16 * (warp & 1) + (lane >> 1);
        const uint4* src = (const uint4*)&g_fin[40 * hg + 4 * cq][1024 * (tg >> 4) + 64 * blk + 4 * (tg & 15)];
        uint4 v[4];
#pragma unroll
        for (int i = 0; i < 4; i++) v[i].x = 0u;
        int spin = 0;
        while (true) {
#pragma unroll
            for (int i = 0; i < 4; i++) if (v[i].x == 0u) v[i] = ld_ll4(src + i * (FP / 4));
            if ((v[0].x && v[1].x && v[2].x && v[3].x) || ++spin >= (1 << 18)) break;
            __nanosleep(FIN_SLEEP);
        }
        TS(21);
        bf16* dst = out + (size_t)(128 * blk + 8 * (tg & 15) + (tg >> 4)) * DM + 80 * hg + 8 * cq;
#pragma unroll
        for (int i = 0; i < 4; i++) stg128(dst + 2 * i * DM, make_uint4(u4(v[0], i), u4(v[1], i), u4(v[2], i), u4(v[3], i)));
    }
    if (bx == 0 && tid == 0) g_epoch = EPOCH + 1;
    TS(22);
    TS_END;
}
typedef CUresult (*EncodeTiledFn)(CUtensorMap*, CUtensorMapDataType, cuuint32_t, void*, const cuuint64_t*, const cuuint64_t*, const cuuint32_t*,
                                  const cuuint32_t*, CUtensorMapInterleave, CUtensorMapSwizzle, CUtensorMapL2promotion, CUtensorMapFloatOOBfill);

static void make_map(EncodeTiledFn enc, CUtensorMap* m, const void* base, int rank, const cuuint64_t* dims, const cuuint64_t* strides,
                     const cuuint32_t* box, CUtensorMapSwizzle sw) {
    cuuint32_t es[4] = {1, 1, 1, 1};
    enc(m, CU_TENSOR_MAP_DATA_TYPE_BFLOAT16, rank, (void*)base, dims, strides, box, es, CU_TENSOR_MAP_INTERLEAVE_NONE, sw,
        sw == CU_TENSOR_MAP_SWIZZLE_128B ? CU_TENSOR_MAP_L2_PROMOTION_L2_128B : CU_TENSOR_MAP_L2_PROMOTION_NONE, CU_TENSOR_MAP_FLOAT_OOB_FILL_NONE);
}

template <typename... KArgs, typename... Args>
static void launch(void (*kern)(KArgs...), int grid, int block, int smem, int cluster, bool pdl, Args... args) {
    cudaLaunchConfig_t cfg = {};
    cfg.gridDim = dim3(grid); cfg.blockDim = dim3(block); cfg.dynamicSmemBytes = smem; cfg.stream = cudaStreamPerThread;
    cudaLaunchAttribute at[2];
    int n = 0;
    if (cluster > 1) { at[n].id = cudaLaunchAttributeClusterDimension; at[n].val.clusterDim.x = cluster; at[n].val.clusterDim.y = 1; at[n].val.clusterDim.z = 1; n++; }
    if (pdl) { at[n].id = cudaLaunchAttributeProgrammaticStreamSerialization; at[n].val.programmaticStreamSerializationAllowed = 1; n++; }
    cfg.attrs = at; cfg.numAttrs = n;
    cudaLaunchKernelEx(&cfg, kern, KArgs(args)...);
}

struct HostState {
    bool ready = false;
    const void* key[4] = {nullptr, nullptr, nullptr, nullptr};
    CUtensorMap mX[2], mRes[2], mW, mWr, mWo, mOut;
    bf16 *x1T, *x2T;
};

extern "C" void kernel_launch(void* const* d_in, const int* in_sizes, int n_in, void* d_out, int out_size) {
    const bf16* x = (const bf16*)d_in[0];
    const bf16* wqkv = (const bf16*)d_in[1];
    const bf16* wo = (const bf16*)d_in[2];
    const bf16* lar = (const bf16*)d_in[4];
    const bf16* aim = (const bf16*)d_in[5];
    const bf16* cre = (const bf16*)d_in[6];
    const bf16* cim = (const bf16*)d_in[7];
    const bf16* logdt = (const bf16*)d_in[8];
    const bf16* dskip = (const bf16*)d_in[9];
    static HostState hs;
    if (!hs.ready || hs.key[0] != wqkv || hs.key[1] != wo || hs.key[2] != x) {
        void* fn = nullptr;
        cudaDriverEntryPointQueryResult qr;
        cudaGetDriverEntryPoint("cuTensorMapEncodeTiled", &fn, cudaEnableDefault, &qr);
        EncodeTiledFn enc = (EncodeTiledFn)fn;
        cudaGetSymbolAddress((void**)&hs.x1T, g_x1T);
        cudaGetSymbolAddress((void**)&hs.x2T, g_x2T);
        {
            cuuint64_t d[3] = {DM, SEQ / 2, 2}, s[2] = {DM * 4, DM * 2};
            cuuint32_t b[3] = {64, 64, 2}, br[3] = {16, 64, 2};
            make_map(enc, &hs.mX[0], x, 3, d, s, b, CU_TENSOR_MAP_SWIZZLE_128B);
            make_map(enc, &hs.mRes[0], x, 3, d, s, br, CU_TENSOR_MAP_SWIZZLE_32B);
            cuuint64_t d2[3] = {SEQ / 2, DM, 2}, s2[2] = {XP * 2, SEQ};
            cuuint32_t b2[3] = {64, 80, 2};
            make_map(enc, &hs.mX[1], hs.x2T, 3, d2, s2, b, CU_TENSOR_MAP_SWIZZLE_128B);
            make_map(enc, &hs.mRes[1], hs.x2T, 3, d2, s2, b2, CU_TENSOR_MAP_SWIZZLE_128B);
            cuuint64_t d3[2] = {SEQ, DM};
            make_map(enc, &hs.mOut, hs.x1T, 2, d3, s2, b2, CU_TENSOR_MAP_SWIZZLE_128B);
        }
        { cuuint64_t d[2] = {3 * DM, DM}, s[1] = {3 * DM * 2}; cuuint32_t b[2] = {64, 32};
          make_map(enc, &hs.mW, wqkv, 2, d, s, b, CU_TENSOR_MAP_SWIZZLE_128B); }
        { cuuint64_t d[3] = {DM, DM, 3}, s[2] = {3 * DM * 2, DM * 2}; cuuint32_t b[3] = {16, 32, 3};
          make_map(enc, &hs.mWr, wqkv, 3, d, s, b, CU_TENSOR_MAP_SWIZZLE_32B); }
        { cuuint64_t d[4] = {8, 8, DM / 8, DM / 8}, s[3] = {DM * 2, 16, DM * 16}; cuuint32_t b[4] = {8, 8, 10, 5};
          make_map(enc, &hs.mWo, wo, 4, d, s, b, CU_TENSOR_MAP_SWIZZLE_NONE); }
        cudaFuncSetAttribute(fused_kernel, cudaFuncAttributeMaxDynamicSharedMemorySize, Q_SMEM);
        hs.key[0] = wqkv; hs.key[1] = wo; hs.key[2] = x;
        hs.ready = true;
    }
    const SsmParams sp = {lar, aim, cre, cim, logdt, dskip};
    launch(fused_kernel, 128, 384, Q_SMEM, 2, false, hs.mX[0], hs.mX[1], hs.mW, hs.mWr, hs.mRes[0], hs.mRes[1], hs.mOut, hs.mWo, (bf16*)d_out, sp);
}
```

```cpp
#include <cuda_runtime.h>
#include <cuda.h>
#include <cuda_bf16.h>
#include <cuda_fp16.h>
#include <stdint.h>

typedef __nv_bfloat16 bf16;

constexpr int SEQ = 2048;
constexpr int DM  = 640;
constexpr int XP  = SEQ + 64;
constexpr int NMODE = 192;

__device__ __forceinline__ uint32_t s2u(const void* p) { return (uint32_t)__cvta_generic_to_shared(p); }
__device__ __forceinline__ void mbar_init(uint32_t b, int c) { asm volatile("mbarrier.init.shared::cta.b64 [%0], %1;" ::"r"(b), "r"(c)); }
__device__ __forceinline__ void mbar_expect(uint32_t b, uint32_t bytes) { asm volatile("mbarrier.arrive.expect_tx.shared::cta.b64 _, [%0], %1;" ::"r"(b), "r"(bytes) : "memory"); }
__device__ __forceinline__ void mbar_arrive(uint32_t b) { asm volatile("mbarrier.arrive.shared::cta.b64 _, [%0];" ::"r"(b) : "memory"); }
__device__ __forceinline__ void mbar_arrive_cta(uint32_t b, uint32_t cta) {
    asm volatile("{\n.reg .b32 ra;\nmapa.shared::cluster.u32 ra, %0, %1;\nmbarrier.arrive.shared::cluster.b64 _, [ra];\n}" ::"r"(b), "r"(cta) : "memory");
}
__device__ __forceinline__ void mbar_wait(uint32_t b, uint32_t ph) {
    asm volatile("{\n.reg .pred p;\n.reg .u32 n;\nmbarrier.try_wait.parity.shared::cta.b64 p, [%0], %1;\n@p bra D;\nmov.u32 n, 0;\n"
                 "W: mbarrier.try_wait.parity.shared::cta.b64 p, [%0], %1;\n@p bra D;\nadd.u32 n, n, 1;\nsetp.lt.u32 p, n, 4194304;\n@p bra W;\ntrap;\nD:\n}"
                 ::"r"(b), "r"(ph) : "memory");
}
__device__ __forceinline__ void fence_mbar_init() { asm volatile("fence.mbarrier_init.release.cluster;" ::: "memory"); }
__device__ __forceinline__ void cluster_sync() { asm volatile("barrier.cluster.arrive.aligned;\nbarrier.cluster.wait.aligned;" ::: "memory"); }
__device__ __forceinline__ void pdl_wait() { asm volatile("griddepcontrol.wait;" ::: "memory"); }
__device__ __forceinline__ void pdl_launch() { asm volatile("griddepcontrol.launch_dependents;" ::: "memory"); }
__device__ __forceinline__ void named_bar(int id, int n) { asm volatile("bar.sync %0, %1;" ::"r"(id), "r"(n) : "memory"); }
__device__ __forceinline__ void fence_async_smem() { asm volatile("fence.proxy.async.shared::cta;" ::: "memory"); }

__device__ __forceinline__ void tma2d(uint32_t dst, const CUtensorMap* m, int c0, int c1, uint32_t bar) {
    asm volatile("cp.async.bulk.tensor.2d.shared::cluster.global.mbarrier::complete_tx::bytes [%0], [%1, {%3, %4}], [%2];"
                 ::"r"(dst), "l"(m), "r"(bar), "r"(c0), "r"(c1) : "memory");
}
__device__ __forceinline__ void tma2d_mc(uint32_t dst, const CUtensorMap* m, int c0, int c1, uint32_t bar, uint16_t mask) {
    asm volatile("cp.async.bulk.tensor.2d.shared::cluster.global.mbarrier::complete_tx::bytes.multicast::cluster [%0], [%1, {%3, %4}], [%2], %5;"
                 ::"r"(dst), "l"(m), "r"(bar), "r"(c0), "r"(c1), "h"(mask) : "memory");
}
__device__ __forceinline__ void tma3d(uint32_t dst, const CUtensorMap* m, int c0, int c1, int c2, uint32_t bar) {
    asm volatile("cp.async.bulk.tensor.3d.shared::cluster.global.mbarrier::complete_tx::bytes [%0], [%1, {%3, %4, %5}], [%2];"
                 ::"r"(dst), "l"(m), "r"(bar), "r"(c0), "r"(c1), "r"(c2) : "memory");
}
__device__ __forceinline__ void tma3d_mc(uint32_t dst, const CUtensorMap* m, int c0, int c1, int c2, uint32_t bar, uint16_t mask) {
    asm volatile("cp.async.bulk.tensor.3d.shared::cluster.global.mbarrier::complete_tx::bytes.multicast::cluster [%0], [%1, {%3, %4, %5}], [%2], %6;"
                 ::"r"(dst), "l"(m), "r"(bar), "r"(c0), "r"(c1), "r"(c2), "h"(mask) : "memory");
}
__device__ __forceinline__ void bulk_g2s(uint32_t dst, const void* src, uint32_t bytes, uint32_t bar) {
    asm volatile("cp.async.bulk.shared::cluster.global.mbarrier::complete_tx::bytes [%0], [%1], %2, [%3];"
                 ::"r"(dst), "l"(src), "r"(bytes), "r"(bar) : "memory");
}
__device__ __forceinline__ void bulk_g2s_mc(uint32_t dst, const void* src, uint32_t bytes, uint32_t bar, uint16_t mask) {
    asm volatile("cp.async.bulk.shared::cluster.global.mbarrier::complete_tx::bytes.multicast::cluster [%0], [%1], %2, [%3], %4;"
                 ::"r"(dst), "l"(src), "r"(bytes), "r"(bar), "h"(mask) : "memory");
}
__device__ __forceinline__ void prefetch_l2(const void* p, uint32_t bytes) { asm volatile("cp.async.bulk.prefetch.L2.global [%0], %1;" ::"l"(p), "r"(bytes) : "memory"); }
__device__ __forceinline__ void prefetch_tmap(const CUtensorMap* m) { asm volatile("prefetch.tensormap [%0];" ::"l"(m) : "memory"); }

__device__ __forceinline__ void wg_fence() { asm volatile("wgmma.fence.sync.aligned;" ::: "memory"); }
__device__ __forceinline__ void wg_commit() { asm volatile("wgmma.commit_group.sync.aligned;" ::: "memory"); }
template <int N> __device__ __forceinline__ void wg_wait() { asm volatile("wgmma.wait_group.sync.aligned %0;" ::"n"(N) : "memory"); }
__device__ __forceinline__ uint64_t mkdesc(uint32_t addr, uint32_t lbo, uint32_t sbo, uint32_t mode) {
    return (uint64_t)((addr & 0x3FFFF) >> 4) | ((uint64_t)(lbo >> 4) << 16) | ((uint64_t)(sbo >> 4) << 32) | ((uint64_t)mode << 62);
}

__device__ __forceinline__ void mma16816(float (&c)[4], uint32_t a0, uint32_t a1, uint32_t a2, uint32_t a3, uint32_t b0, uint32_t b1) {
    asm("mma.sync.aligned.m16n8k16.row.col.f32.bf16.bf16.f32 {%0,%1,%2,%3},{%4,%5,%6,%7},{%8,%9},{%0,%1,%2,%3};"
                 : "+f"(c[0]), "+f"(c[1]), "+f"(c[2]), "+f"(c[3]) : "r"(a0), "r"(a1), "r"(a2), "r"(a3), "r"(b0), "r"(b1));
}
__device__ __forceinline__ void mma1688(float (&c)[4], uint32_t a0, uint32_t a1, uint32_t b0) {
    asm("mma.sync.aligned.m16n8k8.row.col.f32.bf16.bf16.f32 {%0,%1,%2,%3},{%4,%5},{%6},{%0,%1,%2,%3};"
                 : "+f"(c[0]), "+f"(c[1]), "+f"(c[2]), "+f"(c[3]) : "r"(a0), "r"(a1), "r"(b0));
}
__device__ __forceinline__ void ldsm_x4(uint32_t& r0, uint32_t& r1, uint32_t& r2, uint32_t& r3, uint32_t a) {
    asm volatile("ldmatrix.sync.aligned.m8n8.x4.shared.b16 {%0,%1,%2,%3}, [%4];" : "=r"(r0), "=r"(r1), "=r"(r2), "=r"(r3) : "r"(a) : "memory");
}
__device__ __forceinline__ void ldsm_x4_t(uint32_t& r0, uint32_t& r1, uint32_t& r2, uint32_t& r3, uint32_t a) {
    asm volatile("ldmatrix.sync.aligned.m8n8.x4.trans.shared.b16 {%0,%1,%2,%3}, [%4];" : "=r"(r0), "=r"(r1), "=r"(r2), "=r"(r3) : "r"(a) : "memory");
}
__device__ __forceinline__ void ldsm_x2(uint32_t& r0, uint32_t& r1, uint32_t a) {
    asm volatile("ldmatrix.sync.aligned.m8n8.x2.shared.b16 {%0,%1}, [%2];" : "=r"(r0), "=r"(r1) : "r"(a) : "memory");
}
__device__ __forceinline__ void ldsm_x2_t(uint32_t& r0, uint32_t& r1, uint32_t a) {
    asm volatile("ldmatrix.sync.aligned.m8n8.x2.trans.shared.b16 {%0,%1}, [%2];" : "=r"(r0), "=r"(r1) : "r"(a) : "memory");
}
__device__ __forceinline__ void stsm_x4(uint32_t a, uint32_t r0, uint32_t r1, uint32_t r2, uint32_t r3) {
    asm volatile("stmatrix.sync.aligned.m8n8.x4.shared.b16 [%0], {%1,%2,%3,%4};" ::"r"(a), "r"(r0), "r"(r1), "r"(r2), "r"(r3) : "memory");
}
__device__ __forceinline__ void stsm_x4_t(uint32_t a, uint32_t r0, uint32_t r1, uint32_t r2, uint32_t r3) {
    asm volatile("stmatrix.sync.aligned.m8n8.x4.trans.shared.b16 [%0], {%1,%2,%3,%4};" ::"r"(a), "r"(r0), "r"(r1), "r"(r2), "r"(r3) : "memory");
}
__device__ __forceinline__ void stsm_x2(uint32_t a, uint32_t r0, uint32_t r1) {
    asm volatile("stmatrix.sync.aligned.m8n8.x2.shared.b16 [%0], {%1,%2};" ::"r"(a), "r"(r0), "r"(r1) : "memory");
}
__device__ __forceinline__ uint32_t movm_t(uint32_t a) {
    uint32_t d;
    asm volatile("movmatrix.sync.aligned.m8n8.trans.b16 %0, %1;" : "=r"(d) : "r"(a));
    return d;
}
__device__ __forceinline__ uint32_t lds32(uint32_t a) { uint32_t v; asm volatile("ld.shared.u32 %0, [%1];" : "=r"(v) : "r"(a) : "memory"); return v; }
__device__ __forceinline__ uint32_t ldsv32(uint32_t a) { uint32_t v; asm volatile("ld.volatile.shared.u32 %0, [%1];" : "=r"(v) : "r"(a) : "memory"); return v; }
__device__ __forceinline__ void sts32(uint32_t a, uint32_t v) { asm volatile("st.shared.u32 [%0], %1;" ::"r"(a), "r"(v) : "memory"); }
__device__ __forceinline__ uint4 lds128(uint32_t a) { uint4 v; asm volatile("ld.shared.v4.u32 {%0,%1,%2,%3}, [%4];" : "=r"(v.x), "=r"(v.y), "=r"(v.z), "=r"(v.w) : "r"(a) : "memory"); return v; }
__device__ __forceinline__ void sts128(uint32_t a, uint4 v) { asm volatile("st.shared.v4.u32 [%0], {%1,%2,%3,%4};" ::"r"(a), "r"(v.x), "r"(v.y), "r"(v.z), "r"(v.w) : "memory"); }

__device__ __forceinline__ void stg128(void* p, uint4 v) { asm volatile("st.global.v4.u32 [%0], {%1,%2,%3,%4};" ::"l"(p), "r"(v.x), "r"(v.y), "r"(v.z), "r"(v.w) : "memory"); }

__device__ __forceinline__ uint4 ldg128(const void* p) { uint4 v; asm volatile("ld.global.v4.u32 {%0,%1,%2,%3}, [%4];" : "=r"(v.x), "=r"(v.y), "=r"(v.z), "=r"(v.w) : "l"(p) : "memory"); return v; }
__device__ __forceinline__ uint2 ldg64(const void* p) { uint2 v; asm volatile("ld.global.v2.u32 {%0,%1}, [%2];" : "=r"(v.x), "=r"(v.y) : "l"(p) : "memory"); return v; }
__device__ __forceinline__ uint32_t ldg32(const void* p) { uint32_t v; asm volatile("ld.global.u32 %0, [%1];" : "=r"(v) : "l"(p) : "memory"); return v; }

__device__ __forceinline__ uint32_t pack2(float lo, float hi) {
    uint32_t r;
    asm("cvt.rn.bf16x2.f32 %0, %1, %2;" : "=r"(r) : "f"(hi), "f"(lo));
    return r;
}
__device__ __forceinline__ float bf_lo(uint32_t v) { return __uint_as_float(v << 16); }
__device__ __forceinline__ float bf_hi(uint32_t v) { return __uint_as_float(v & 0xFFFF0000u); }
__device__ __forceinline__ float rbf(float x) { return __uint_as_float(pack2(0.f, x) & 0xFFFF0000u); }
__device__ __forceinline__ float ex2(float x) { float r; asm("ex2.approx.ftz.f32 %0, %1;" : "=f"(r) : "f"(x)); return r; }

__device__ __forceinline__ float2 ln_finish(float sum, float sumsq) {
    const float m = sum * (1.0f / DM);
    const float v = fmaxf(fmaf(sumsq, 1.0f / DM, -m * m), 0.f);
    float s, r;
    asm("sqrt.approx.ftz.f32 %0, %1;" : "=f"(s) : "f"(rbf(rbf(v) + 1e-5f)));
    asm("rcp.approx.ftz.f32 %0, %1;" : "=f"(r) : "f"(rbf(s)));
    return make_float2(m, r);
}
__device__ __forceinline__ uint32_t ln_finish_packed(float sum, float sumsq) {
    const float m = sum * (1.0f / DM);
    const float v = fmaxf(fmaf(sumsq, 1.0f / DM, -m * m), 0.f);
    float s;
    asm("sqrt.approx.ftz.f32 %0, %1;" : "=f"(s) : "f"(rbf(rbf(v) + 1e-5f)));
    return pack2(s, m);
}
__device__ __forceinline__ float frsq(float x) { float r; asm("rsqrt.approx.ftz.f32 %0, %1;" : "=f"(r) : "f"(x)); return r; }
__device__ __forceinline__ float frcp(float x) { float r; asm("rcp.approx.ftz.f32 %0, %1;" : "=f"(r) : "f"(x)); return r; }
__device__ __forceinline__ bool elect_one() {
    uint32_t p;
    asm volatile("{\n.reg .pred p;\nelect.sync _|p, 0xffffffff;\nselp.u32 %0, 1, 0, p;\n}" : "=r"(p));
    return p != 0;
}
__device__ __forceinline__ void cluster_arrive_relaxed() { asm volatile("barrier.cluster.arrive.relaxed.aligned;" ::: "memory"); }
__device__ __forceinline__ void cluster_wait() { asm volatile("barrier.cluster.wait.aligned;" ::: "memory"); }
__device__ __forceinline__ unsigned long long ld_ll(const unsigned long long* p) {
    unsigned long long v;
    asm volatile("ld.relaxed.gpu.global.b64 %0, [%1];" : "=l"(v) : "l"(p) : "memory");
    return v;
}
__device__ __forceinline__ void st_ll(unsigned long long* p, uint32_t payload, uint32_t tag) {
    const unsigned long long v = (unsigned long long)payload | ((unsigned long long)tag << 32);
    asm volatile("st.relaxed.gpu.global.b64 [%0], %1;" ::"l"(p), "l"(v) : "memory");
}
__device__ __forceinline__ uint4 ld_ll4(const uint4* p) {
    uint4 v;
    asm volatile("{\n.reg .b128 t;\n.reg .b64 a, b;\nld.relaxed.gpu.global.b128 t, [%4];\nmov.b128 {a, b}, t;\nmov.b64 {%0, %1}, a;\nmov.b64 {%2, %3}, b;\n}"
                 : "=r"(v.x), "=r"(v.y), "=r"(v.z), "=r"(v.w) : "l"(p) : "memory");
    return v;
}
__device__ __forceinline__ void st_ll4(uint4* p, uint32_t x, uint32_t y, uint32_t z, uint32_t w) {
    asm volatile("{\n.reg .b128 t;\n.reg .b64 a, b;\nmov.b64 a, {%1, %2};\nmov.b64 b, {%3, %4};\nmov.b128 t, {a, b};\nst.relaxed.gpu.global.b128 [%0], t;\n}"
                 ::"l"(p), "r"(x), "r"(y), "r"(z), "r"(w) : "memory");
}

__device__ __forceinline__ void bulk_s2g(void* dst, uint32_t src, uint32_t bytes) {
    asm volatile("cp.async.bulk.global.shared::cta.bulk_group [%0], [%1], %2;" ::"l"(dst), "r"(src), "r"(bytes) : "memory");
}
__device__ __forceinline__ void bulk_commit() { asm volatile("cp.async.bulk.commit_group;" ::: "memory"); }
__device__ __forceinline__ void bulk_wait() { asm volatile("cp.async.bulk.wait_group 0;" ::: "memory"); }
__device__ __forceinline__ void fence_async_global() { asm volatile("fence.proxy.async.global;" ::: "memory"); }
__device__ __forceinline__ void fence_release() { asm volatile("fence.release.gpu;" ::: "memory"); }
__device__ __forceinline__ void fence_acquire() { asm volatile("fence.acquire.gpu;" ::: "memory"); }
template<int TA, int TB>
__device__ __forceinline__ void wgmma_n192(float (&d)[96], uint64_t da, uint64_t db, int scale_d) {
  asm volatile("{\n.reg .pred p;\nsetp.ne.b32 p, %98, 0;\n"
    "wgmma.mma_async.sync.aligned.m64n192k16.f32.bf16.bf16 "
    "{%0, %1, %2, %3, %4, %5, %6, %7, %8, %9, %10, %11, %12, %13, %14, %15, %16, %17, %18, %19, %20, %21, %22, %23, %24, %25, %26, %27, %28, %29, %30, %31, %32, %33, %34, %35, %36, %37, %38, %39, %40, %41, %42, %43, %44, %45, %46, %47, %48, %49, %50, %51, %52, %53, %54, %55, %56, %57, %58, %59, %60, %61, %62, %63, %64, %65, %66, %67, %68, %69, %70, %71, %72, %73, %74, %75, %76, %77, %78, %79, %80, %81, %82, %83, %84, %85, %86, %87, %88, %89, %90, %91, %92, %93, %94, %95}, %96, %97, p, 1, 1, %99, %100;\n}\n"
    : "+f"(d[0]), "+f"(d[1]), "+f"(d[2]), "+f"(d[3]), "+f"(d[4]), "+f"(d[5]), "+f"(d[6]), "+f"(d[7]), "+f"(d[8]), "+f"(d[9]), "+f"(d[10]), "+f"(d[11]), "+f"(d[12]), "+f"(d[13]), "+f"(d[14]), "+f"(d[15]), "+f"(d[16]), "+f"(d[17]), "+f"(d[18]), "+f"(d[19]), "+f"(d[20]), "+f"(d[21]), "+f"(d[22]), "+f"(d[23]), "+f"(d[24]), "+f"(d[25]), "+f"(d[26]), "+f"(d[27]), "+f"(d[28]), "+f"(d[29]), "+f"(d[30]), "+f"(d[31]), "+f"(d[32]), "+f"(d[33]), "+f"(d[34]), "+f"(d[35]), "+f"(d[36]), "+f"(d[37]), "+f"(d[38]), "+f"(d[39]), "+f"(d[40]), "+f"(d[41]), "+f"(d[42]), "+f"(d[43]), "+f"(d[44]), "+f"(d[45]), "+f"(d[46]), "+f"(d[47]), "+f"(d[48]), "+f"(d[49]), "+f"(d[50]), "+f"(d[51]), "+f"(d[52]), "+f"(d[53]), "+f"(d[54]), "+f"(d[55]), "+f"(d[56]), "+f"(d[57]), "+f"(d[58]), "+f"(d[59]), "+f"(d[60]), "+f"(d[61]), "+f"(d[62]), "+f"(d[63]), "+f"(d[64]), "+f"(d[65]), "+f"(d[66]), "+f"(d[67]), "+f"(d[68]), "+f"(d[69]), "+f"(d[70]), "+f"(d[71]), "+f"(d[72]), "+f"(d[73]), "+f"(d[74]), "+f"(d[75]), "+f"(d[76]), "+f"(d[77]), "+f"(d[78]), "+f"(d[79]), "+f"(d[80]), "+f"(d[81]), "+f"(d[82]), "+f"(d[83]), "+f"(d[84]), "+f"(d[85]), "+f"(d[86]), "+f"(d[87]), "+f"(d[88]), "+f"(d[89]), "+f"(d[90]), "+f"(d[91]), "+f"(d[92]), "+f"(d[93]), "+f"(d[94]), "+f"(d[95])
    : "l"(da), "l"(db), "r"(scale_d), "n"(TA), "n"(TB));
}

template<int TA, int TB>
__device__ __forceinline__ void wgmma_n48(float (&d)[24], uint64_t da, uint64_t db, int scale_d) {
  asm volatile("{\n.reg .pred p;\nsetp.ne.b32 p, %26, 0;\n"
    "wgmma.mma_async.sync.aligned.m64n48k16.f32.bf16.bf16 "
    "{%0, %1, %2, %3, %4, %5, %6, %7, %8, %9, %10, %11, %12, %13, %14, %15, %16, %17, %18, %19, %20, %21, %22, %23}, %24, %25, p, 1, 1, %27, %28;\n}\n"
    : "+f"(d[0]), "+f"(d[1]), "+f"(d[2]), "+f"(d[3]), "+f"(d[4]), "+f"(d[5]), "+f"(d[6]), "+f"(d[7]), "+f"(d[8]), "+f"(d[9]), "+f"(d[10]), "+f"(d[11]), "+f"(d[12]), "+f"(d[13]), "+f"(d[14]), "+f"(d[15]), "+f"(d[16]), "+f"(d[17]), "+f"(d[18]), "+f"(d[19]), "+f"(d[20]), "+f"(d[21]), "+f"(d[22]), "+f"(d[23])
    : "l"(da), "l"(db), "r"(scale_d), "n"(TA), "n"(TB));
}

__device__ __forceinline__ void wgmma_rs80(float (&d)[40], const uint4& a, uint64_t db, int scale_d) {
  asm volatile("{\n.reg .pred p;\nsetp.ne.b32 p, %45, 0;\n"
    "wgmma.mma_async.sync.aligned.m64n80k16.f32.bf16.bf16 {%0,%1,%2,%3,%4,%5,%6,%7,%8,%9,%10,%11,%12,%13,%14,%15,%16,%17,%18,%19,%20,%21,%22,%23,%24,%25,%26,%27,%28,%29,%30,%31,%32,%33,%34,%35,%36,%37,%38,%39}, {%40,%41,%42,%43}, %44, p, 1, 1, 1;\n}\n"
    : "+f"(d[0]), "+f"(d[1]), "+f"(d[2]), "+f"(d[3]), "+f"(d[4]), "+f"(d[5]), "+f"(d[6]), "+f"(d[7]), "+f"(d[8]), "+f"(d[9]), "+f"(d[10]), "+f"(d[11]), "+f"(d[12]), "+f"(d[13]), "+f"(d[14]), "+f"(d[15]), "+f"(d[16]), "+f"(d[17]), "+f"(d[18]), "+f"(d[19]), "+f"(d[20]), "+f"(d[21]), "+f"(d[22]), "+f"(d[23]), "+f"(d[24]), "+f"(d[25]), "+f"(d[26]), "+f"(d[27]), "+f"(d[28]), "+f"(d[29]), "+f"(d[30]), "+f"(d[31]), "+f"(d[32]), "+f"(d[33]), "+f"(d[34]), "+f"(d[35]), "+f"(d[36]), "+f"(d[37]), "+f"(d[38]), "+f"(d[39])
    : "r"(a.x), "r"(a.y), "r"(a.z), "r"(a.w), "l"(db), "r"(scale_d));
}

__device__ const __align__(1024) uint32_t c_fft[11264] = {
0x2ddc2dba,0x2fe62eb5,0x2ed02eb5,0xafffaf6e,0x2e1f2dfe,0x2e3f2fbc,0x2f022ee9,0xad27af30,0x2e5e2e3f,0x1fd92b5e,0x2f302f1a,0x244ea875,0x2e992e7c,0xad96a993,0x2f5a2f46,0x2e992c32,
0xad00ad72,0xa17eac32,0xa17ea515,0xabb79cb6,0xac07ac87,0x2dfe29f1,0x1fd99648,0xafedae99,0xa9f1ab05,0x2fd42fbc,0x26a1244e,0xad96af91,0xa765a8d5,0x2aaa2e3f,0x29932875,0x2515a8d5,
0xae99adfe,0xb000aee9,0xaf6eafbc,0x2c872f30,0xaf80af1a,0xac32af02,0xae7caf02,0xaaaa217e,0xaff4afc9,0x2b5e9cb6,0xad27addc,0xaff4ae7c,0xafedb000,0x2ffc2eb5,0xab05ac5d,0xacd8af5a,
0x2c072d27,0x9fd92bb7,0xadfead00,0x2fed2e1f,0x25db2993,0xaf6eacb0,0xaf6eaed0,0x2c5d2f46,0xa5151648,0xaddcafdd,0xafffafd4,0xac321648,0xabb7a934,0x28d5a814,0xafa0afed,0xaff4af30,
0x2f302e3f,0x2fed2f1a,0x28142b5e,0x2934a875,0x30002fc9,0x26a12ddc,0xa5db1cb6,0x30002e7c,0x2f462fd4,0xaed0aa4e,0xacb0aa4e,0x29932e99,0x2d272e5e,0xae3faffc,0xaf02adfe,0xae1fa814,
0xa9f1acd8,0x26a1ab05,0x2fd42ffc,0xad96afed,0x2515a30e,0x2fff2e1f,0x2ddc2f1a,0x2c32a30e,0x2d272aaa,0x28752e7c,0x28752c32,0x2fa02f80,0x2f912e99,0xaee9a9f1,0xa8141648,0x9fd92c87,
0xafa0ae7c,0xafafaf46,0x2d002993,0xafa0ac32,0xaf91b000,0x244eac5d,0x2fbc2eb5,0xab05af5a,0xac87ae5e,0x30002dfe,0x2f6e2ffc,0x2e992814,0x1cb6a875,0x25152e1f,0x2c322e1f,0x2d722ff4,
0x27652c87,0xa9932a4e,0xaaaaadba,0xa5152c87,0xabb7a44e,0xafa0af30,0x28d59fd9,0xaff4ae5e,0xaf91ae1f,0x2814abb7,0x2ee92d00,0x1fd9ad27,0xaf5aafff,0x2fd42ed0,0x2fd42fe6,0x30002ddc,
0x2f462f6e,0x2c322fdd,0x2e7c2fdd,0xa993b000,0xab5e2934,0xafafacd8,0xad00244e,0x2f1a2dfe,0xaee9afaf,0x2f30a17e,0xadfeaff8,0xafbca30e,0x2c5da765,0xa9f12ddc,0x2d969cb6,0x2c5dacb0,
0x2bb7a993,0x2f1aa515,0x2f1a2765,0xaff4aaaa,0x2e5e2fd4,0xab052dba,0x29342f6e,0x2ee9a6a1,0xadba1fd9,0xa5dbafed,0xafddac07,0xaa4e2dfe,0xacb0aff8,0x2ddc2f02,0x9cb6ae3f,0xa765aff8,
0xaeb5af91,0xaa4eafed,0x9648ae5e,0xac5d2d4d,0x2ddca17e,0x2e7c2e3f,0x2fc92e3f,0x1cb6afa0,0x2bb72fe6,0xaff8a993,0xab5e2aaa,0x2bb72fc9,0xafbcaa4e,0x2f30a5db,0xadfeafdd,0xaee9adba,
0xacd828d5,0xaf91230e,0xaf30af02,0x2c072fa0,0xac5dafff,0x2dbaac32,0x2dbaa515,0xae99addc,0x2fc929f1,0xa9932eb5,0x2aaa2fdd,0x2fe629f1,0xa30e2dfe,0xa17eafed,0xaff8ac07,0xafaf1fd9,
0x2dfe2faf,0x28142ff8,0xae5e217e,0x2ffc230e,0xaf5aa515,0xac87af46,0xa6a1af80,0xaf5a2765,0x1cb6ae99,0x2e7c2dba,0x2fc92dba,0x2ddcac5d,0x2f1a2ee9,0xafafab05,0xad002934,0xab5e2e5e,
0x2dbaa814,0x2fdd9fd9,0x25db2f91,0x2a4eaee9,0x27652faf,0xaf4628d5,0xaf80ae1f,0xa5152faf,0xafa0addc,0x2e3fac32,0x2e3fa515,0xa17eafff,0x2dfea6a1,0xacd82dba,0x244e2f6e,0x29342fd4,
0xad27afc9,0xa30eafff,0x2faf2d72,0xad27ae7c,0x2ffc2a4e,0x28142fdd,0xae5e25db,0x2dfe2dba,0xac5d2c07,0xaa4eaf91,0x9648af30,0xaeb5acd8,0xa993aff4,0x2c322f1a,0x2e7c2f1a,0x2f462bb7,
0xae7c26a1,0xafff1648,0x2d72aa4e,0xafc926a1,0x230eaee9,0x2ff89fd9,0x217e2f91,0x2fafa814,0x2d4d2fa0,0xafed230e,0xae5eaf02,0xaf9128d5,0xb000aaaa,0x2fdda515,0x2fdd2765,0x2f6ea993,
0x9cb63000,0xacb02fd4,0xa7652fd4,0x2ddcaf5a,0x217eaffc,0x2ff4ac07,0x2875afbc,0xaff82934,0xa44e2ff4,0xadfea8d5,0xa9342fa0,0x2cd82bb7,0x25dbafe6,0x16482f46,0x29f1af80,0x25dbafc9,
0x2ff41cb6,0x2e1f2765,0x2e1f2cb0,0xa875addc,0xafbca5db,0x1fd9af5a,0xad4dad96,0xacd82fdd,0x2f5a2934,0xaeb52ee9,0x2c5d2e5e,0x3000ab05,0xaed0ab5e,0x2f80a30e,0xaaaaaf02,0xacb0ab5e,
0x25dbaffc,0x2d96afbc,0x2f5aac07,0xafdd2934,0xaaaa2fa0,0xafc92875,0xafe62875,0x29932d27,0x2d00aed0,0x28d52d72,0x2ff89cb6,0x2d00afe6,0xae5e2d96,0x2d4dafd4,0xaf91a6a1,0xafed29f1,
0xafbca17e,0xad4da875,0x1fd9aff4,0xacd82ff8,0x2e992aaa,0xaa4e2fe6,0xaa4e2fc9,0x2fd4a993,0xacb0ad96,0x2fffac87,0x2d72aeb5,0xa765ad96,0x28752f30,0xab5eac07,0xaf1a2cd8,0xae3f2f91,
0xa9342ff4,0xae5e2fa0,0xaee9a8d5,0x2b052bb7,0x2d96aed0,0x2eb59cb6,0x2c872d72,0x2d96afe6,0xaf802c5d,0x2765af6e,0xa515af6e,0xaf4625db,0x2ff8a44e,0xaff42d4d,0xa8752ffc,0xa17e2ee9,
0x2f5a244e,0x2c5d2934,0xaeb52dfe,0x3000acd8,0xacb0ad00,0x2d72aff8,0x2fffa8d5,0xa765ad00,0x217e2f80,0xaf022515,0xaf02a765,0xaf1a2f46,0x2b05afdd,0xa8142f5a,0x2c072d96,0x2d4d25db,
0x2b5eafe6,0x2f02af80,0x230e2f46,0x2b5eafc9,0xaf302d96,0xacd8a6a1,0x2c07afd4,0xaf9129f1,0x2fdda44e,0xad962ffc,0xaf5a2d4d,0xa5db2ee9,0xad72abb7,0x2e7ca17e,0x2fc9a17e,0x2fffad00,
0xaed0a5db,0xaaaaa9f1,0x2f809648,0xacb0a5db,0x28752e5e,0xaf1a2f91,0xab5ead4d,0xae3f2fed,0x2b05aff8,0x2c072875,0xa8142ff4,0x2d4d217e,0xaf6e2d72,0x2eb5afc9,0x2eb5ae7c,0x2dbaafff,
0xaf802f5a,0xafc92e99,0xafe62e99,0x2f46ad96,0x28d52b05,0xaf022fed,0x230e2cd8,0x2fa0affc,0x2fbcaf02,0xa9342d27,0x2ffcae1f,0x2c07ae3f,0xa6a1ac32,0x2a4e9cb6,0x9648ad72,0xa6a1a515,
0x28752aaa,0xa8d52cb0,0xa8d52ed0,0x2e3faf80,0x2fedaeb5,0x29349648,0x2f30aa4e,0x2814ac5d,0x1648ad4d,0x2e99acd8,0x2c87afbc,0xa9f11fd9,0xafe62d27,0x2fffafaf,0xaddc230e,0xaed02d27,
0x2fd4af30,0x2f6eae5e,0x2dbaa44e,0xa6a19fd9,0x1cb6ad27,0x2fe6aff4,0x2ed0aff4,0xad722b5e,0xafaf2cb0,0x2e1faf46,0xa8d5a993,0xafaf2ed0,0xac072f6e,0x2934ac87,0xaffc2e99,0xafbc3000,
0xa44eab5e,0x2b05ad00,0x2f91afaf,0xafbc2f1a,0xafd42d72,0x1648a765,0x1648acb0,0xafdd2fff,0xac322f5a,0xaaaa26a1,0xaf802c87,0xae7c2f5a,0x2d009fd9,0xae1f2cd8,0xad272fbc,0xabb72d4d,
0xaffc2f02,0xaee92e1f,0x244ead27,0xad4d2e3f,0xa9f12e7c,0xafdd2f80,0xaeb52aaa,0xa9f12c32,0x2d72a5db,0xafe63000,0xaed03000,0x9cb626a1,0x2fa0afbc,0xaf022f91,0x230e2b05,0x28d5a44e,
0x96482c07,0xac872d4d,0xae992b05,0x29f1a814,0x2ed0abb7,0xa9932b5e,0xaf462ff8,0x2cb0abb7,0x2f1aafff,0xa30e2765,0xa30e2cb0,0x2e1fad72,0x1fd9ac5d,0x244e9648,0x2e5eaa4e,0x2f30aeb5,
0x2ff8aed0,0x2e3faddc,0xaf022fff,0x2ff8afe6,0x2d4daf6e,0x2ee9ae99,0xa44e2c87,0x2ffcb000,0xa6a1a814,0x2f6eaf30,0x2dbaa934,0x2fd4afed,0xaf462d00,0x2fc9afa0,0x2fe6afa0,0x2f80afaf,
0x2515ac5d,0x2d72ad96,0x1cb629f1,0x2c32ac5d,0xad002814,0x2d27ad4d,0x2e1fab05,0x2bb7ac07,0xaffc2f1a,0x2cd8ad00,0x2fedafaf,0x2b05ab5e,0xadba2f80,0x2c87acb0,0x2c87aed0,0x2a4eaaaa,
0x2f802f6e,0x2fc92fdd,0x2fe62fdd,0xaf46b000,0x2fa02f91,0x2bb72e5e,0x2ff42fed,0xa8d5ad4d,0x2fbc2faf,0xa934217e,0x2ffc2ff8,0x2c07230e,0x2fd42fc9,0xaf5aad72,0x30002fff,0x2fd42e7c,
0x2bb72aaa,0x2f1a2cb0,0x2f1a2ed0,0xaff4af80,0x2cd82c5d,0x2f303000,0x2f912f5a,0xac07aeb5,0x2dba2d4d,0x25db2cd8,0x2fdd2fbc,0x2a4e9fd9,0x2e7c2e1f,0xad72a875,0x2fff2ff4,0x2fc92e1f,
0xa6a1a934,0x29f1a44e,0x2d962cd8,0xafd4adfe,0x1cb6a17e,0x2fe62e3f,0x2ed02e3f,0xad72afa0,0x28752515,0x2d272f80,0x2fa02f46,0x2875a765,0x2c072a4e,0xa93425db,0x2ffc2fdd,0x2fbc2dba,
0xae5eaf1a,0xa934ae3f,0x2b052875,0xaee9ab5e,0xac5dad72,0x2dba2765,0x2dba2cb0,0xae99afff,0xa765aa4e,0x2f802fd4,0x2f462e99,0x2515aa4e,0x230e9fd9,0x217e2cd8,0x2ff82fbc,0x2faf2d4d,
0xaffcafaf,0xaee9aff8,0x244ea17e,0xad4da30e,0xaf6eafe6,0x25dbaaaa,0x2c5d2993,0xaf6eafc9,0xad72ae99,0x2fe62dba,0x2ed02dba,0x1cb6ac5d,0xa8d5ac07,0x2bb72f30,0x2ff42f91,0x2fa02cd8,
0xadbaac07,0xafddad4d,0xa5dbab05,0xaa4e2814,0xafc9af02,0xaaaaaf1a,0x2993217e,0xafe6af02,0xafa0afff,0x2e3f2765,0x2e3f2cb0,0xa17ead72,0xad4daeb5,0x2e5e3000,0x2fed2f5a,0x2f912c5d,
0xa17e2765,0xad001cb6,0xabb7addc,0xa17e2cb0,0xad4daa4e,0xaee9afdd,0x244ea5db,0xaffcadba,0xafd4aee9,0x29f1a934,0x2d962b05,0xa6a1ae5e,0xaf46aff4,0x2fc92f1a,0x2fe62f1a,0x2f802bb7,
0x2cb02eb5,0x1cb62dba,0xaddcaf6e,0x27652eb5,0xa30e2814,0xaff8ad4d,0xa17eab05,0xafafac07,0xadfeab5e,0xa44eae3f,0x2cd82875,0xa934af1a,0xb000af80,0x2fdd2cb0,0x2fdd2ed0,0x2f6e2aaa,
0x2d723000,0x25152fd4,0x2c322fd4,0x1cb6af5a,0xae1f9fd9,0xae3faee9,0xaf02a814,0x2d272f91,0xacd8aff4,0x2ffc28d5,0xab05afa0,0xafedabb7,0x2e992515,0xad962aaa,0x2f5a2993,0x2e99a765,
0x2ff42ddc,0x2e1f2ed0,0x2e1f2fe6,0xa875afff,0xa8142c87,0xaffca9f1,0xadfe1648,0x2e5e2e99,0xaf5aaf30,0x2eb5a814,0xac5dafed,0xb000a934,0x2c32a8d5,0xa9932e3f,0x2f462875,0x2e7ca8d5,
0x2e991fd9,0x30002814,0x2f6e2ee9,0xac87af91,0x29932fa0,0xaed02875,0xacb02875,0x2f462d27,0xaff4ac32,0x2b5eaddc,0xad27afff,0xaff4a515,0x244ead96,0x1fd92fd4,0x2f3026a1,0x2e5ea9f1,
0x2814ad27,0x2dfeabb7,0x2ffc2d00,0xae5eae1f,0x2e992f80,0xaa4e2e7c,0xaa4e2c32,0x2fd42aaa,0xae7c1648,0x9cb6afdd,0xaddcafd4,0xafc91648,0xa875af91,0x2b5e2fbc,0x2f1a244e,0x2e3fab05,
0xab05aff4,0x244eafa0,0x2fbc28d5,0xaf91abb7,0x30002c32,0x26a12fff,0xa5db2ddc,0x30002515,0xaaaa2c5d,0xac32af6e,0xae7caf6e,0xaf8025db,0xad27afed,0x2e3f2dfe,0x2f021fd9,0x2e1fac07,
0xaf5aae5e,0xac5daf30,0x2eb59fd9,0xb000a44e,0x2e7ca30e,0x2ddc2e1f,0x1cb62f1a,0x2fc9a30e,0x217e2f46,0xaf02acb0,0xaf02aed0,0xaf1a2993,0xaf30ae99,0x2fbc29f1,0x2ee99648,0x2dfeac87,
0xafa0a515,0xafafa993,0x2d00aaaa,0xafa02765,0x2934ad96,0x2fed26a1,0x28142fd4,0x2f30a9f1,0x2c872fed,0xb0009fd9,0xaf6eadfe,0xae992c07,0xafffabb7,0x2fe6a17e,0x2ed0a17e,0x2ddcad00,
0xac322c87,0xaf462a4e,0x2993adba,0xae7c2c87,0xa875afed,0x2f1aab05,0x2b5e2ffc,0x2e3facd8,0x2f302e1f,0xaee92bb7,0xafbcad00,0xadfe2d27,0xaf6e9cb6,0x2eb5ac32,0x2eb5a515,0x2dbaad72,
0xaaaa2f5a,0xaed02e99,0xacb02e99,0x2f80ad96,0x2b5eaf30,0x2fafa44e,0x2d00ae5e,0xaf1a9fd9,0xac072f02,0xab05ad27,0xad4d2e1f,0x28142e3f,0x2c5daed0,0xa9f12fff,0x2d96addc,0x2c5dafe6,
0x28752f80,0xa8d52fe6,0xa8d52fc9,0x2e3faf46,0xa44eafd4,0x2f91adba,0x2b05af6e,0xafbc26a1,0x96482ffc,0xae99a44e,0xac872ee9,0x29f12d4d,0x2515aff8,0x1cb62f02,0x2d72ae3f,0x2c32aff8,
0x2eb52b05,0x2a4e2cd8,0x16482fed,0x2c5daffc,0xad72ad27,0x2cb0aff4,0x2765aff4,0xafff2b5e,0x2bb72e7c,0xaff82aaa,0xab5e2f80,0x2bb72c32,0xa814af6e,0x2b052c87,0x2d4dae99,0x2c07b000,
0x2feda8d5,0x2f30a30e,0x29342f02,0x2814afa0,0xafd49cb6,0x1648aed0,0x1648afe6,0xafdd2d72,0x2ed029f1,0xaf462eb5,0xa9932fdd,0x2cb029f1,0xad00ad4d,0x2e1f244e,0x2d27aee9,0x2bb7affc,
0x2d4daf02,0x2fbcae1f,0x2cd82d27,0x9fd9ae3f,0xaf5a2cb0,0xac87a993,0xa6a1af46,0xaf5a2ed0,0x2fffa5db,0xacb03000,0xa7653000,0x2d7226a1,0xaf1aa814,0x2fafa934,0x2d00af30,0x2b5eafed,
0x1648afbc,0x2c87affc,0x2e992934,0xa9f1ac07,0xac322faf,0xaf8028d5,0xaaaaae1f,0xae7c2faf,0x2f1aad72,0xa30e2ed0,0xa30e2fe6,0x2e1f1cb6,0xaffc26a1,0x2fedadba,0x2cd8af6e,0x2b05afd4,
0xad27ac32,0xa30ead72,0x2faf9cb6,0xad27a515,0x1fd92f6e,0xafbc2e99,0xacd8ac87,0xad4d3000,0x2c5dafbc,0x2a4e2b05,0x16482f91,0x2eb5a44e,0xaf802d00,0x2ed0afa0,0x2cb0afa0,0x2aaaafaf,
0xafe626a1,0xaddc1648,0x2fffaa4e,0xaed026a1,0x2d002c07,0xad272ffc,0xae1fa934,0xabb72fbc,0x1fd9afa0,0x2e5ea30e,0x244e2f02,0x2f30a8d5,0xadba2f46,0x2c87afe6,0x2c87afc9,0x2a4eaf80,
0xafff2d96,0xae7c2c5d,0xafc92c5d,0x2d72a9f1,0xa17e2dfe,0xaff42fbc,0xa8752ee9,0x2ff8af30,0x2fedad00,0xad4d2f1a,0x2f91ab5e,0x2e5eafaf,0x25dbae7c,0x16482993,0x29f1af46,0x25dbac32,
0xae3f2fff,0xaff82fc9,0xaff82e7c,0x2f02ad72,0x2c0725db,0xadfe2f5a,0x9fd92d96,0x2fedafdd,0x2f6eaf91,0xa6a12c07,0x2fd4acd8,0x2dbaaf30,0xa765ab5e,0x2aaaa30e,0x2993af02,0x2515ab5e,
0xa5db2dfe,0xad962ee9,0xaf5a2fbc,0x2fddaf30,0x2f46ab5e,0xa7652bb7,0x25152bb7,0x2f80aff8,0x2d00afc9,0x28d59cb6,0x2ff8addc,0x2d00ae7c,0xacd89648,0x2dfeac5d,0x2934aeb5,0x244eaa4e,
0x2c07217e,0x9fd92875,0xadfe2ff4,0x2fedaff8,0x2fddaf46,0x29f1a515,0x29f12765,0x2eb5af80,0x2515ad96,0x2ddcac87,0x2fffaeb5,0x2c32ad96,0xaf022b05,0x2fa0aee9,0x28d5ae5e,0x230ea934,
0x2f91ad00,0x2cd8ab5e,0xac072f1a,0x2f30afaf,0x2d96afc9,0x2eb5addc,0x2c879cb6,0x2d96ae7c,0xa993a6a1,0x2fc9af5a,0x2fe6af5a,0x2aaaac87,0xaff82e5e,0x2ff4affc,0x2875adfe,0x217ea814,
0x2f6eafed,0x2fd4af91,0xa6a12d4d,0x2dbaae5e,0x2515ad00,0x2fffaff8,0x2ddca8d5,0x2c32ad00,0xae1f2993,0x2fafafe6,0x2fafafc9,0x28d5aaaa,0xaf912fdd,0x2ee9af5a,0x2814ad96,0x1fd9a5db,
0x2b5eae7c,0x2f02af46,0x230e2993,0x2b5eac32,0xab059648,0x2e5eaeb5,0x2ee9ac5d,0x2934aa4e,0xafdd2e5e,0x2d96adfe,0x2f5aaffc,0x25dba814,0xaddc2faf,0x2cb0ad27,0x2765ad27,0x1cb6a30e,
0xa765a5db,0x2993a9f1,0x2aaa9648,0x2515a5db,0xaf022cd8,0x28d5a934,0x2fa0adfe,0x230ea44e,0xaf912ff8,0x2814a875,0x2ee9aff4,0x1fd9a17e,0xaa4e2ddc,0x26a1a765,0x26a1acb0,0x16489cb6,
0x2d722d96,0x25152c5d,0x2c322c5d,0x1cb6a9f1,0x2d272d4d,0xad00a814,0x2bb72c07,0x2e1f2b05,0x2cd82d00,0xaffcaf1a,0x2b052b5e,0x2fed2faf,0x2c872cb0,0xadbaaf80,0x2a4e2aaa,0x2c872ed0,
0x2e3f2ddc,0x2ff82ed0,0x2ff82fe6,0xaf02afff,0x2ee92e99,0x2d4d2f6e,0x2ffc3000,0xa44eac87,0x2f6e2f30,0xa6a12814,0x2fd42fed,0x2dba2934,0x2fc92fa0,0xaf46ad00,0x2f802faf,0x2fe62fa0,
0xac87ad4d,0x9648ac07,0x29f12814,0xae99ab05,0xa993ab5e,0x2ed02bb7,0x2cb02bb7,0xaf46aff8,0xa30ea765,0x2f1a2fff,0x2e1f2d72,0xa30eacb0,0x244e1648,0x1fd92c5d,0x2f302eb5,0x2e5e2a4e,
0xaee9ae1f,0xaffcaf02,0xad4dae3f,0x244e2d27,0xafddaf80,0xa9f1ae7c,0xa9f1ac32,0xaeb5aaaa,0xafe6b000,0x2d7225db,0x9cb6a6a1,0xaed0b000,0xaf02af91,0x2fa02fbc,0x28d5244e,0x230eab05,
0x2b052d00,0xa44e2b5e,0xafbcaf1a,0x2f912faf,0x16482765,0xafd4ad72,0xafddafff,0x16482cb0,0xaaaaa6a1,0xac32af5a,0xae7caf5a,0xaf80ac87,0xae1facd8,0x2d001fd9,0xabb7ad4d,0xad27afbc,
0x2f6e2e5e,0x2fd42f30,0xa6a11fd9,0x2dba244e,0x2fe62ff4,0x1cb62d27,0xad72ab5e,0x2ed02ff4,0x2e1f2f46,0xafafacb0,0xafafaed0,0xa8d52993,0x29342c87,0xac07af6e,0xafbcb000,0xaffcae99,
0xa8d5acb0,0x2875aaaa,0x2e3f2f80,0xa8d5aed0,0x29341648,0x2fed2eb5,0x28142c5d,0x2f302a4e,0x2e992cd8,0x16482d4d,0xa9f19fd9,0x2c872fbc,0x2fff2faf,0xafe6ad27,0xaed0ad27,0xaddca30e,
0xafc9ae99,0xaf80af5a,0x2f462d96,0xafe6ae99,0xaf02afed,0x28d5ab05,0x2fa02ffc,0x230eacd8,0xa934ad27,0x2fbc2f02,0x2c072e3f,0x2ffc2e1f,0x2a4e1cb6,0xa6a12c32,0xa6a12515,0x96482d72,
0xaaaa29f1,0xaed025db,0xacb025db,0x2f801648,0xaf1aaf91,0x2875ae5e,0xae3fafed,0xab5e2d4d,0x2c07a875,0x2b052ff8,0x2d4da17e,0xa814aff4,0x2eb52fc9,0xaf6ead72,0x2dba2fff,0x2eb52e7c,
0x2f022f80,0x2b5e2fe6,0x2b5e2fc9,0x230eaf46,0xacd826a1,0xaf30ad96,0xaf91a9f1,0x2c072fd4,0xad96affc,0x2fdd244e,0xa5dbaee9,0xaf5aad4d,0x2e7c217e,0xad722bb7,0x2fff2d00,0x2fc9217e,
0x2c5da934,0x2f5aa44e,0x30002cd8,0xaeb5adfe,0x2d722ff8,0xacb02d00,0xa7652d00,0x2fff28d5,0xaf02a515,0x217eaf80,0xaf1aaf46,0xaf022765,0xa814af5a,0x2b052fdd,0x2d4da5db,0x2c07ad96,
0xae5eafa0,0xa934aff4,0x2b05abb7,0xaee928d5,0x2eb51cb6,0x2d962ed0,0x2d962fe6,0x2c87ad72,0x27652f6e,0xaf80ac5d,0xaf46a5db,0xa5152f6e,0xaff4ad4d,0x2ff8244e,0xa17eaee9,0xa875affc,
0xad4d2875,0xafbc217e,0xacd8aff8,0x1fd92ff4,0xaa4eafe6,0x2e99aaaa,0x2fd42993,0xaa4eafc9,0x2fff2c87,0xacb02d96,0xa7652d96,0x2d722eb5,0xab5e2c07,0x2875af30,0xae3faf91,0xaf1aacd8,
0x2d962fbc,0x25db2ffc,0xafdda934,0x2f5a2c07,0xafc9a875,0xaaaaafa0,0x2993ad27,0xafe6a875,0x28d5ad72,0x2d002ed0,0x2d002fe6,0x2ff81cb6,0x2d4d2fd4,0xae5ead96,0xafeda9f1,0xaf9126a1,
0x2e1fa765,0x2ff49cb6,0xa8752ddc,0x2e1facb0,0x1fd92f5a,0xafbc25db,0xacd8afdd,0xad4d2d96,0xaeb5aee9,0x2f5aa934,0x30002b05,0x2c5dae5e,0x2f80230e,0xaed02b5e,0xacb02b5e,0xaaaa2f02,
0xacb0afd4,0x9cb6b000,0x2ddc2f5a,0xa765afd4,0x2ff42c07,0x217e2ffc,0xaff8a934,0x28752fbc,0xadfe28d5,0xa44eaff4,0x2cd8abb7,0xa934afa0,0x1648af46,0x25db2fe6,0x25db2fc9,0x29f12f80,
0xafff9648,0xae7ca6a1,0xafc9a6a1,0x2d722a4e,0x2ff81fd9,0x230e2ee9,0x2faf2814,0x217eaf91,0xafeda30e,0x2d4dafa0,0xaf91a8d5,0xae5e2f02,0x2fdd2515,0xb0002aaa,0x2f6e2993,0x2fdda765,
0xa30e2fff,0xad272fc9,0xad272e7c,0x2fafad72,0x2814afdd,0x2ffcaa4e,0x2dfeadba,0xae5ea5db,0xaa4e2f91,0xac5dac07,0xaeb52cd8,0x96482f30,0x2c32af1a,0xa9932ff4,0x2f46abb7,0x2e7caf1a,
0x2fdd1fd9,0x2dba2814,0x2a4e2ee9,0x25dbaf91,0xaf46a8d5,0x2765afaf,0xa515afaf,0xaf802e1f,0x2e3f2c32,0xafa02ddc,0xa17e2fff,0x2e3f2515,0xacd8adba,0x2dfe26a1,0x2934afd4,0x244eaf6e,
0x2814aff8,0x2dfeafaf,0x2ffca30e,0xae5ea17e,0xac872f46,0xaf5a2515,0xaf5aa765,0xa6a12f80,0x2e7cadba,0x1cb62e99,0x2ddc2c5d,0x2fc9adba,0xafaf2b05,0x2f1aaee9,0xab5eae5e,0xad00a934,
0xaf91a30e,0xacd8a8d5,0x2c07afa0,0xaf302f02,0x2dba2c32,0xac5d2fff,0xae992ddc,0x2dba2515,0xa993aeb5,0x2fc9a9f1,0x2fe6a9f1,0x2aaaafdd,0xa17e2fed,0xa30eadfe,0xafaf9fd9,0xaff82c07,
0xaa4e2fed,0xaeb52f91,0xac5dad4d,0x96482e5e,0x2e7cae3f,0x2ddc217e,0x1cb62fa0,0x2fc9ae3f,0xaff82993,0x2bb7afe6,0x2bb7afc9,0xab5eaaaa,0x2f3025db,0xafbc2a4e,0xaee92dba,0xadfe2fdd,
0x2f1a2515,0x2bb72993,0xaff42aaa,0x2f1aa765,0xab05adba,0x2e5eafd4,0x2ee926a1,0x2934af6e,0xa5db2fed,0xadba9fd9,0xaa4eadfe,0xafdd2c07,0x2ddcaf02,0xacb02ff8,0xa7652ff8,0x9cb62e3f,
0x2c32afdd,0x2f46af6e,0xa9933000,0x2e7cafdd,0xafaf2cd8,0xab5ea934,0x2f1aadfe,0xad00a44e,0x2f30217e,0xaee92faf,0xafbc230e,0xadfe2ff8,0xa9f1addc,0x2c5d2765,0x2c5d2cb0,0x2d961cb6,
0xa993aa4e,0x2765ac87,0xa515ac87,0xaaaa2dba,0xafa02f30,0xabb7244e,0xaff42e5e,0x28d51fd9,0x28142bb7,0xaf912e1f,0x1fd92d27,0x2ee9ad00,0x2fd4aed0,0xaf5a2fff,0x3000addc,0x2fd4afe6,
0xafaf2f46,0xafa02e7c,0xafa02c32,0x2d00a993,0x244e2c5d,0xaf913000,0xab052f5a,0x2fbcaeb5,0x3000adfe,0xac872e5e,0x2e99a814,0x2f6eaffc,0x2515ae1f,0x1cb62875,0x2d72aff4,0x2c32ae1f,
0x26a12b05,0xa9f12cd8,0xad962fed,0x2fd4affc,0x2fffae1f,0x2515230e,0x2c32230e,0x2ddcaf1a,0x2875ae7c,0x2d27aaaa,0x2fa0af80,0x2875ac32,0xaee929f1,0x2f91ae99,0x9fd9ac87,0xa8149648,
0x2fedaf1a,0x2f30ae3f,0x29342875,0x2814ab5e,0x26a1addc,0x3000afc9,0x3000ae7c,0xa5db9cb6,0xaed02a4e,0x2f46afd4,0x2993ae99,0xacb02a4e,0xae3f2ffc,0x2d27ae5e,0xae1f2814,0xaf022dfe,
0x9fd9abb7,0x2c07ad27,0x2fedae1f,0xadfe2d00,0xaf6e2cb0,0x25dba993,0x2c5daf46,0xaf6e2ed0,0xaddc2fdd,0xa5159648,0xac329648,0xafff2fd4,0x28d52814,0xabb72934,0xaff42f30,0xafa02fed,
0xb0002ee9,0xae992dfe,0x2c87af30,0xaf6e2fbc,0xac322f02,0xaf802f1a,0xaaaaa17e,0xae7c2f02,0x2b5e1cb6,0xaff42fc9,0xaff42e7c,0xad272ddc,0x2ffcaeb5,0xafed3000,0xacd82f5a,0xab052c5d,
0xa17e2c32,0xad002d72,0xabb71cb6,0xa17e2515,0x2dfea9f1,0xac072c87,0xafed2e99,0x1fd91648,0x2fd4afbc,0xa9f12b05,0xad962f91,0x26a1a44e,0x2aaaae3f,0xa76528d5,0x251528d5,0x2993a875,
0x2fe6aeb5,0x2ddcadba,0xafff2f6e,0x2ed0aeb5,0x2e3fafbc,0x2e1fadfe,0xad272f30,0x2f02aee9,0x1fd9ab5e,0x2e5eae3f,0x244e2875,0x2f30af1a,0xad962993,0x2e99ae7c,0x2e99ac32,0x2f5aaf46,
0x299329f1,0xa76525db,0x251525db,0x2aaa1648,0x28d52934,0xaf02acd8,0x230e244e,0x2fa02dfe,0x28142875,0xaf91aff8,0x1fd9217e,0x2ee92ff4,0x26a12765,0xaa4eaddc,0x16481cb6,0x26a12cb0,
0x2f022f46,0x2b5e2e7c,0x2b5e2c32,0x230ea993,0x2e5e2eb5,0xab051648,0x29342a4e,0x2ee92c5d,0x2d962dfe,0xafddae5e,0x25db2814,0x2f5a2ffc,0x2cb02d27,0xaddcafaf,0x1cb6230e,0x27652d27,
0x2fd42f91,0x2f6e2fed,0x2dba2e5e,0xa6a1ad4d,0x2fff2ff8,0x25152d00,0x2c322d00,0x2ddc28d5,0x2faf2fe6,0xae1fa993,0x28d52aaa,0x2faf2fc9,0x2ee92f5a,0xaf91afdd,0x1fd925db,0x28142d96,
0x2cd82b5e,0x2f912d00,0x2f302faf,0xac07af1a,0x2eb52ddc,0x2d962fc9,0x2d962e7c,0x2c871cb6,0x2fc92f5a,0xa99326a1,0x2aaa2c87,0x2fe62f5a,0x2ff42ffc,0xaff8ae5e,0x217e2814,0x28752dfe,
0x9fd9a875,0x2c07a17e,0x2fed2ff8,0xadfeaff4,0x29f12515,0x2fdd2f46,0x2eb52f80,0x29f1a765,0x2ddc2c87,0x25152d96,0x2c322d96,0x2fff2eb5,0x2fa02ee9,0xaf02ab05,0x230e2934,0x28d52e5e,
0xad96aee9,0xa5dbadfe,0x2fdd2f30,0xaf5aafbc,0xa765abb7,0x2f462b5e,0x2f802ff8,0x2515abb7,0x28d51cb6,0x2d002fc9,0x2d002e7c,0x2ff82ddc,0x2dfe2c5d,0xacd81648,0x244e2a4e,0x29342eb5,
0xaff8afc9,0xae3fafff,0x2f022d72,0xaff8ae7c,0xadfeaf5a,0x2c07a5db,0x2fed2fdd,0x9fd9ad96,0xa6a1ac07,0x2f6e2f91,0x2dba2f30,0x2fd42cd8,0x2aaa230e,0xa7652b5e,0x25152b5e,0x29932f02,
0xae7cac5d,0xafffad96,0x2d7229f1,0xafc9ac5d,0xaff4afbc,0xa17eadfe,0x2ff82f30,0xa875aee9,0xad4daf1a,0x2fed2d00,0x2e5e2faf,0x2f912b5e,0x1648a993,0x25db2e7c,0x25db2c32,0x29f12f46,
0xaddc9648,0xafe6a6a1,0xaed0a6a1,0x2fff2a4e,0xad27affc,0x2d00ac07,0xabb7afbc,0xae1f2934,0x2e5e230e,0x1fd92fa0,0x2f3028d5,0x244eaf02,0x2c872fe6,0xadbaaf46,0x2a4e2f80,0x2c872fc9,
0xa30e2d72,0xad272c32,0xad272515,0x2faf1cb6,0xafbcae99,0x1fd9af6e,0xad4db000,0xacd82c87,0x2a4eab05,0x2c5d2fbc,0x2eb5244e,0x1648af91,0x2ed02fa0,0xaf80ad00,0x2aaa2faf,0x2cb02fa0,
0x2c872ffc,0x16482fbc,0xa9f12c07,0x2e99a934,0xaf80a8d5,0xac32afaf,0xae7cafaf,0xaaaa2e1f,0xa30eaed0,0x2f1a2d72,0x2e1f9cb6,0xa30eafe6,0x2fed2dba,0xaffca6a1,0x2b052fd4,0x2cd82f6e,
0x2fbc2e1f,0x2d4d2f02,0x9fd92e3f,0x2cd8ad27,0xac872993,0xaf5aacb0,0xaf5aaed0,0xa6a12f46,0xacb0b000,0x2fff25db,0x2d72a6a1,0xa765b000,0x2faf2934,0xaf1a2814,0x2b5e2fed,0x2d002f30,
0x2f30230e,0x2fed28d5,0x28142fa0,0x2934af02,0x16482ed0,0xafd41cb6,0xafddad72,0x16482fe6,0xaf46aeb5,0x2ed0a9f1,0x2cb0a9f1,0xa993afdd,0x2e1fa44e,0xad002d4d,0x2bb72ffc,0x2d272ee9,
0x2a4eacd8,0x2eb5ab05,0x2c5d2ffc,0x1648afed,0x2cb02ff4,0xad722d27,0xafffab5e,0x27652ff4,0xaff8aaaa,0x2bb7ae7c,0x2bb7ac32,0xab5eaf80,0x2b05ac87,0xa8142f6e,0x2c073000,0x2d4d2e99,
0xa8d5afe6,0x2875af80,0x2e3f2f46,0xa8d5afc9,0x2f912dba,0xa44e2fd4,0xafbca6a1,0x2b052f6e,0xae99244e,0x9648affc,0x29f1ad4d,0xac87aee9,0x1cb6af02,0x25152ff8,0x2c322ff8,0x2d722e3f,
0xaed0ae99,0xaaaaaf5a,0x2f802d96,0xacb0ae99,0x2faf244e,0x2b5e2f30,0xaf1a1fd9,0x2d002e5e,0xab052d27,0xac07af02,0x2814ae3f,0xad4dae1f,0xa9f1afff,0x2c5d2ed0,0x2c5d2fe6,0x2d962ddc,
0xaf46aa4e,0xac32ac87,0xae7cac87,0x29932dba,0x2f1a2b05,0xa8752fed,0x2e3f2cd8,0x2b5eaffc,0xaee9abb7,0x2f30ae1f,0xadfead27,0xafbc2d00,0x2eb52c32,0xaf6e1cb6,0x2dba2d72,0x2eb52515,
0xafaf2993,0xafa02515,0xafa0a765,0x2d002aaa,0x2feda6a1,0x29342d96,0x2f3029f1,0x2814afd4,0xb0001fd9,0x2c87afed,0xae99ac07,0xaf6e2dfe,0x2fe6217e,0xafff2bb7,0x2ddc2d00,0x2ed0217e,
0xac5d2f30,0xaf5a2e5e,0xb000244e,0x2eb51fd9,0x2ddcae1f,0x2e7c230e,0x2fc9230e,0x1cb6af1a,0xaf022cb0,0x217eaf46,0xaf1aa993,0xaf022ed0,0x2fbca9f1,0xaf302e99,0x2dfe2c87,0x2ee91648,
0x244e2fa0,0xab052ff4,0xaf912bb7,0x2fbca8d5,0x26a1afff,0x3000ac32,0x3000a515,0xa5dbaddc,0xac322f6e,0xaaaaac5d,0xaf80a5db,0xae7c2f6e,0x2e3fadfe,0xad272fed,0x2e1f2c07,0x2f029fd9,
0x2dfe2bb7,0x28142d27,0xae5e2e1f,0x2ffcad00,0xaa4eae7c,0x2e99af80,0x2fd4aaaa,0xaa4eac32,0x9cb62fdd,0xae7c9648,0xafc99648,0xaddc2fd4,0x2b5eafbc,0xa8752f91,0x2e3f2b05,0x2f1aa44e,
0x3000a814,0x2e999fd9,0xac872f91,0x2f6eaee9,0xaed0a875,0x2993afa0,0x2f46ad27,0xacb0a875,0x2b5e2ddc,0xaff42c32,0xaff42515,0xad272fff,0x1fd9afd4,0x244e2d96,0x2e5e29f1,0x2f30a6a1,
0x2e1faed0,0x2ff4addc,0xa8752fff,0x2e1fafe6,0xaffc29f1,0xa814ac87,0x2e5eae99,0xadfe9648,0x2eb52814,0xaf5a2f30,0xb0002934,0xac5d2fed,0xa993ae3f,0x2c3228d5,0x2e7c28d5,0x2f46a875,
0x2515afd4,0x2d72b000,0x1cb62f5a,0x2c32afd4,0xae3f2ee9,0xae1f1fd9,0x2d27af91,0xaf022814,0x2ffca8d5,0xacd82ff4,0xafed2bb7,0xab052fa0,0xad96aaaa,0x2e99a515,0x2e992765,0x2f5aa993,
0x1cb6adba,0x2cb0aeb5,0x2765aeb5,0xaddc2f6e,0xaff82d4d,0xa30ea814,0xafaf2c07,0xa17e2b05,0xa44e2e3f,0xadfe2b5e,0xa9342f1a,0x2cd8a875,0x2fddacb0,0xb0002f80,0x2f6eaaaa,0x2fddaed0,
0xad009cb6,0xa17ea765,0xa17eacb0,0xabb72ddc,0xaee92fdd,0xad4d2a4e,0xaffc2dba,0x244e25db,0x29f12934,0xafd42ee9,0xa6a12e5e,0x2d96ab05,0x2fc9af1a,0xaf462ff4,0x2f80abb7,0x2fe6af1a,
0xafdd2d4d,0xadba2c07,0xaa4ea814,0xa5db2b05,0xaaaa2f1a,0xafc92f02,0xafe62f02,0x2993a17e,0x2e3fa765,0xafa02fff,0xa17e2d72,0x2e3facb0,0x2e5eb000,0xad4d2eb5,0x2f91ac5d,0x2fedaf5a,
0xaee92ff8,0xaffc2faf,0xad4d230e,0x244e217e,0x25db2aaa,0xaf6e2fe6,0xaf6e2fc9,0x2c5da993,0x2fe6adba,0xad722e99,0x1cb62c5d,0x2ed0adba,0x2bb7af30,0xa8d52c07,0x2fa0acd8,0x2ff4af91,
0xa9342e3f,0xae5e2f1a,0xaee92b5e,0x2b05a875,0x2dbaa765,0xac5d2d72,0xae992fff,0x2dbaacb0,0x2f80afd4,0xa7652a4e,0x25152a4e,0x2f46ae99,0x217eacd8,0x230e1fd9,0x2fafad4d,0x2ff8afbc,
0x29f1244e,0xa6a12934,0xafd42dfe,0x2d96acd8,0x2fe6ae3f,0x1cb6217e,0xad722fa0,0x2ed0ae3f,0x2d27af80,0x2875a515,0x28752765,0x2fa0af46,0xa934a5db,0x2c07aa4e,0x2fbcadba,0x2ffcafdd,
0x2f1aacb0,0x2bb7aaaa,0xaff42f80,0x2f1aaed0,0x2f30b000,0x2cd8ac5d,0xac072eb5,0x2f91af5a,0x25dbacd8,0x2dbaad4d,0x2a4e1fd9,0x2fddafbc,0xad722875,0x2e7cae1f,0x2fc9ae1f,0x2fffaff4,
0x2fc9afdd,0x2f80af6e,0xaf463000,0x2fe6afdd,0x2bb7ae5e,0x2fa0af91,0xa8d52d4d,0x2ff4afed,0xa934a17e,0x2fbcafaf,0x2c07a30e,0x2ffcaff8,0xaf5a2d72,0x2fd4afc9,0x2fd4ae7c,0x3000afff,
0x3c003c00,0x3bff3c00,0x3c003c00,0x3bfa3bfd,0x3c003c00,0x3bef3bf5,0x3c003c00,0x3bde3be7,0x3c003c00,0x3bc83bd4,0x3c003c00,0x3bac3bbb,0x3c003c00,0x3b8b3b9d,0x3bff3c00,0x3b653b79,
0x3c003c00,0x3bff3c00,0x3c003c00,0x3bf83bfd,0x3bff3c00,0x3bea3bf2,0x3bff3bff,0x3bd63be1,0x3bfe3bff,0x3bba3bc9,0x3bfd3bfe,0x3b983baa,0x3bfc3bfd,0x3b6f3b84,0x3bfb3bfc,0x3b3f3b58,
0x3c003c00,0x3bff3c00,0x3bff3c00,0x3bf63bfc,0x3bfe3bff,0x3be53bef,0x3bfd3bfe,0x3bcc3bda,0x3bfb3bfc,0x3bab3bbc,0x3bf93bfa,0x3b813b97,0x3bf63bf7,0x3b4f3b69,0x3bf23bf4,0x3b163b33,
0x3c003c00,0x3bff3c00,0x3bff3c00,0x3bf53bfb,0x3bfd3bfe,0x3be03bec,0x3bfa3bfc,0x3bc23bd2,0x3bf63bf8,0x3b9a3baf,0x3bf23bf4,0x3b683b82,0x3bec3bef,0x3b2c3b4b,0x3be53be9,0x3ae83b0b,
0x3c003c00,0x3bfe3c00,0x3bfe3bff,0x3bf23bfa,0x3bfb3bfd,0x3bda3be8,0x3bf63bf9,0x3bb73bca,0x3bf03bf4,0x3b873ba0,0x3be83bed,0x3b4c3b6b,0x3bdf3be4,0x3b073b2b,0x3bd43bda,0x3ab63ae0,
0x3c003c00,0x3bfe3c00,0x3bfd3bff,0x3bf03bf9,0x3bf93bfb,0x3bd43be4,0x3bf23bf6,0x3bab3bc1,0x3be83bed,0x3b733b91,0x3bdd3be3,0x3b2f3b53,0x3bcf3bd6,0x3ade3b08,0x3bbf3bc7,0x3a813ab1,
0x3c003c00,0x3bfe3c00,0x3bfc3bfe,0x3bee3bf8,0x3bf63bf9,0x3bce3be0,0x3bec3bf1,0x3b9e3bb7,0x3bdf3be6,0x3b5e3b80,0x3bcf3bd7,0x3b103b39,0x3bbc3bc6,0x3ab33ae3,0x3ba53bb1,0x3a493a7f,
0x3bff3c00,0x3bfe3c00,0x3bfb3bfe,0x3beb3bf7,0x3bf23bf7,0x3bc63bdb,0x3be53bed,0x3b903bad,0x3bd43bdd,0x3b473b6e,0x3bbf3bca,0x3aee3b1d,0x3ba53bb2,0x3a853abc,0x3b873b97,0x3a0d3a4b,
0x3bfd3c00,0x3bfa3c00,0x3be83bf6,0x3bcc3be9,0x3bbf3bd6,0x3b713ba4,0x3b813ba2,0x3aeb3b33,0x3b2f3b5a,0x3a3d3a99,0x3acb3aff,0x396b39d8,0x3a543a92,0x387a38f6,0x39cd3a13,0x36dd37ee,
0x3bfd3c00,0x3bfa3c00,0x3be53bf4,0x3bc83be7,0x3bb73bd1,0x3b653b9d,0x3b713b97,0x3ad53b22,0x3b163b46,0x3a193a7c,0x3aa53ae0,0x393739ad,0x3a213a65,0x383538ba,0x398b39d8,0x36313753,
0x3bfd3c00,0x3bf93c00,0x3be23bf3,0x3bc33be5,0x3bae3bcb,0x3b593b95,0x3b603b8a,0x3abd3b11,0x3afb3b30,0x39f43a5e,0x3a7e3abf,0x39023980,0x39eb3a37,0x37dd387c,0x3946399b,0x358136b5,
0x3bfc3c00,0x3bf93c00,0x3bdf3bf1,0x3bbf3be3,0x3ba53bc6,0x3b4c3b8c,0x3b4f3b7d,0x3aa53aff,0x3ade3b1a,0x39cd3a3f,0x3a543a9c,0x38cc3951,0x39b33a07,0x374e383d,0x38fd395b,0x34cf3614,
0x3bfc3c00,0x3bf83c00,0x3bdc3bf0,0x3bba3be1,0x3b9c3bc0,0x3b3f3b84,0x3b3d3b70,0x3a8c3aed,0x3ac13b02,0x39a63a1f,0x3a293a78,0x38943922,0x397939d4,0x36bb37f9,0x38b23918,0x341a3570,
0x3bfc3c00,0x3bf83c00,0x3bd83bee,0x3bb53bdf,0x3b923bb9,0x3b323b7b,0x3b2a3b62,0x3a733ad9,0x3aa23ae9,0x397d39fe,0x39fc3a52,0x385a38f1,0x393c399f,0x36253775,0x386538d3,0x32c634c9,
0x3bfb3c00,0x3bf73c00,0x3bd43bed,0x3bb03bdc,0x3b873bb2,0x3b243b72,0x3b163b53,0x3a583ac6,0x3a813ad0,0x395439dc,0x39cd3a2b,0x382038bf,0x38fd3969,0x358d36ee,0x3815388c,0x31533420,
0x3bfb3c00,0x3bf63c00,0x3bd03beb,0x3bab3bda,0x3b7c3bab,0x3b163b69,0x3b013b43,0x3a3d3ab1,0x3a603ab5,0x392939ba,0x399d3a02,0x37c8388c,0x38bc3930,0x34f33665,0x37853842,0x2fbd32ea,
0x3bf63c00,0x3bf03c00,0x3ba53bd7,0x3b733bc1,0x3b073b5f,0x3a813b08,0x3a213a9c,0x392939e1,0x38fd3996,0x36ff385d,0x374e3858,0x327c3529,0x345735da,0xa9b12d1a,0x2cce3191,0xb49fb160,
0x3bf53c00,0x3bef3c00,0x3b9f3bd5,0x3b6c3bbe,0x3af73b55,0x3a6f3afc,0x3a043a87,0x390739c7,0x38d13972,0x36993832,0x36d23822,0x316c34b1,0x3371354c,0xad65297f,0x27763036,0xb552b2b9,
0x3bf53c00,0x3bef3c00,0x3b9a3bd2,0x3b653bbb,0x3ae83b4b,0x3a5c3af0,0x39e73a71,0x38e539ad,0x38a3394d,0x36313807,0x365437d8,0x305b3438,0x323234bd,0xafef1e48,0xa4522db0,0xb602b408,
0x3bf43c00,0x3bee3c00,0x3b943bd0,0x3b5e3bb7,0x3ad83b41,0x3a493ae3,0x39c93a5a,0x38c13992,0x38743927,0x35c837b7,0x35d4376a,0x2e91337d,0x30f0342c,0xb13ba7da,0xac0629e3,0xb6afb4b1,
0x3bf33c00,0x3bed3c00,0x3b8e3bcd,0x3b573bb4,0x3ac73b36,0x3a353ad6,0x39aa3a43,0x389e3976,0x38453900,0x355e375e,0x355236f9,0x2c6a3288,0x2f593334,0xb27cac51,0xaef51a48,0xb759b558,
0x3bf23c00,0x3bec3c00,0x3b873bca,0x3b4f3bb1,0x3ab63b2b,0x3a213ac9,0x398b3a2b,0x387a395b,0x381538d8,0x34f33705,0x34cf3687,0x28843191,0x2cce320d,0xb3baaeaa,0xb0f0a91b,0xb7feb5fd,
0x3bf23c00,0x3beb3c00,0x3b813bc7,0x3b473bad,0x3aa53b20,0x3a0d3abc,0x396b3a13,0x3855393e,0x37c838b0,0x348736aa,0x344b3614,0x16483099,0x288430e4,0xb47bb080,0xb263ad4c,0xb850b69e,
0x3bf13c00,0x3bea3c00,0x3b7a3bc4,0x3b3f3baa,0x3a933b14,0x39f83aae,0x394a39fa,0x38303922,0x37643887,0x341a364e,0x3389359f,0xa81f2f40,0x9cb62f72,0xb517b1aa,0xb3d3b004,0xb89eb73d,
0x3be93c00,0x3be13c00,0x3b373ba6,0x3af13b86,0x39e33aa0,0x392e3a27,0x380a3905,0x3599380d,0x335935f1,0x217f31db,0xac382d4c,0xb546b12e,0xb5b1b2d2,0xb90cb7cd,0xb8eab7d8,0xbadbba0b,
0x3be83c00,0x3be03c00,0x3b2f3ba2,0x3ae83b82,0x39cd3a92,0x39163a17,0x37c838e7,0x354637d8,0x327c3593,0xa4523115,0xae5f2aac,0xb5c8b226,0xb648b3f7,0xb94ab828,0xb933b838,0xbb0aba43,
0x3be73c00,0x3bdf3c00,0x3b273b9e,0x3ade3b7d,0x39b83a83,0x38fd3a07,0x377a38c9,0x34f33796,0x319e3534,0xa9b1304e,0xb042257f,0xb648b31b,0xb6ddb48d,0xb986b867,0xb979b881,0xbb35ba78,
0x3be63c00,0x3bde3c00,0x3b1e3b9b,0x3ad53b79,0x39a13a74,0x38e539f6,0x372c38ab,0x349f3753,0x30be34d5,0xac9c2f0e,0xb153a0b6,0xb6c6b408,0xb76fb51d,0xb9c0b8a6,0xb9bcb8c9,0xbb5cbaaa,
0x3be53c00,0x3bdd3c00,0x3b163b97,0x3acb3b74,0x398b3a65,0x38cc39e5,0x36dd388c,0x344b3710,0x2fbd3475,0xae5f2d7e,0xb263a91b,0xb742b481,0xb7feb5ab,0xb9f8b8e2,0xb9fcb90e,0xbb7fbad9,
0x3be43c00,0x3bdc3c00,0x3b0d3b93,0x3ac13b70,0x39743a56,0x38b239d4,0x368d386d,0x33eb36cc,0x2dfb3414,0xb0102bd9,0xb371ac83,0xb7bdb4f9,0xb845b637,0xba2db91d,0xba39b951,0xbb9ebb05,
0x3be33c00,0x3bda3c00,0x3b043b8f,0x3ab63b6b,0x395d3a47,0x389939c3,0x363c384d,0x33403687,0x2c383365,0xb0f028b6,0xb43eae78,0xb81ab570,0xb889b6c1,0xba60b956,0xba73b992,0xbbb8bb2e,
0x3be23c00,0x3bd93c00,0x3afb3b8a,0x3aac3b67,0x39463a37,0x387f39b1,0x35eb382d,0x32943642,0x28e832a1,0xb1cf2248,0xb4c3b036,0xb855b5e5,0xb8ccb748,0xba90b98d,0xbaa9b9d0,0xbbcfbb53,
0x3c003c00,0x3bfe3c00,0x3c003c00,0x3bf73bfc,0x3c003c00,0x3beb3bf2,0x3c003c00,0x3bd93be3,0x3c003c00,0x3bc13bce,0x3c003c00,0x3ba53bb4,0x3c003c00,0x3b823b94,0x3bff3bff,0x3b5b3b6f,
0x3c003c00,0x3bfe3c00,0x3c003c00,0x3bf53bfb,0x3bff3c00,0x3be63bee,0x3bff3bff,0x3bcf3bdb,0x3bfe3bfe,0x3bb23bc1,0x3bfd3bfe,0x3b8e3ba1,0x3bfc3bfd,0x3b643b7a,0x3bfb3bfb,0x3b333b4c,
0x3c003c00,0x3bfe3c00,0x3bff3c00,0x3bf33bf9,0x3bfe3bff,0x3be03beb,0x3bfd3bfd,0x3bc53bd3,0x3bfb3bfc,0x3ba13bb4,0x3bf83bf9,0x3b753b8c,0x3bf53bf7,0x3b413b5c,0x3bf23bf3,0x3b063b25,
0x3c003c00,0x3bfd3c00,0x3bff3bff,0x3bf03bf8,0x3bfc3bfe,0x3bda3be6,0x3bf93bfb,0x3bb93bca,0x3bf53bf7,0x3b8e3ba5,0x3bf03bf3,0x3b5a3b75,0x3beb3bee,0x3b1c3b3c,0x3be43be7,0x3ad53afa,
0x3c003c00,0x3bfd3c00,0x3bfe3bff,0x3bee3bf7,0x3bfa3bfc,0x3bd33be2,0x3bf53bf8,0x3bac3bc1,0x3bee3bf2,0x3b7a3b94,0x3be63beb,0x3b3c3b5c,0x3bdd3be2,0x3af43b19,0x3bd13bd7,0x3aa13acb,
0x3bff3c00,0x3bfc3c00,0x3bfc3bfe,0x3beb3bf5,0x3bf73bfa,0x3bcb3bdd,0x3bf03bf4,0x3b9e3bb6,0x3be63beb,0x3b643b82,0x3bda3be0,0x3b1c3b41,0x3bcb3bd3,0x3ac83af4,0x3bba3bc3,0x3a683a9a,
0x3bff3c00,0x3bfb3bff,0x3bfb3bfd,0x3be73bf3,0x3bf43bf8,0x3bc33bd7,0x3be93bef,0x3b8f3bab,0x3bdb3be3,0x3b4c3b6f,0x3bca3bd3,0x3afa3b25,0x3bb63bc1,0x3a9a3acb,0x3b9f3bab,0x3a2c3a65,
0x3bff3c00,0x3bfb3bff,0x3bf93bfd,0x3be43bf2,0x3bf03bf5,0x3bba3bd1,0x3be23be9,0x3b7f3b9f,0x3bcf3bd9,0x3b333b5b,0x3bb93bc5,0x3ad53b06,0x3b9e3bac,0x3a683aa1,0x3b7f3b8f,0x39ec3a2c,
0x3bfa3bff,0x3bf33bff,0x3be03bf0,0x3bba3bdc,0x3bb13bcb,0x3b533b8c,0x3b6e3b92,0x3ac33b10,0x3b183b45,0x3a0c3a6c,0x3aaf3ae5,0x393139a3,0x3a343a73,0x383938b9,0x39a939f1,0x36513767,
0x3bf93bff,0x3bf23bfe,0x3bdc3bee,0x3bb43bd9,0x3ba73bc5,0x3b453b82,0x3b5c3b85,0x3aa93afd,0x3afb3b2e,0x39e43a4c,0x3a863ac3,0x38fa3973,0x39fd3a44,0x37e03878,0x396339b2,0x359c36c3,
0x3bf93bff,0x3bf13bfe,0x3bd83beb,0x3bae3bd6,0x3b9d3bbe,0x3b373b78,0x3b493b76,0x3a8f3ae9,0x3add3b16,0x39bb3a2a,0x3a5b3a9f,0x38c03942,0x39c43a12,0x374b3836,0x39193971,0x34e4361d,
0x3bf83bff,0x3bf03bfe,0x3bd33be9,0x3ba73bd3,0x3b923bb6,0x3b273b6e,0x3b353b67,0x3a733ad4,0x3abe3afd,0x39913a08,0x3a2e3a79,0x38853910,0x398839de,0x36b237e6,0x38cd392d,0x34293573,
0x3bf73bff,0x3bee3bfe,0x3bcf3be7,0x3ba13bcf,0x3b873baf,0x3b183b64,0x3b203b57,0x3a573abe,0x3a9d3ae2,0x396539e4,0x39ff3a51,0x384938dc,0x394939a7,0x3617375c,0x387e38e6,0x32d834c6,
0x3bf63bff,0x3bed3bfe,0x3bca3be4,0x3b9a3bcc,0x3b7b3ba6,0x3b073b58,0x3b0a3b47,0x3a3a3aa8,0x3a7b3ac6,0x393939bf,0x39cf3a28,0x380b38a7,0x3908396e,0x357936cf,0x382c389d,0x315a3417,
0x3bf53bff,0x3bec3bfe,0x3bc53be2,0x3b933bc8,0x3b6e3b9e,0x3af73b4d,0x3af43b35,0x3a1c3a91,0x3a573aa9,0x390b399a,0x399c39fd,0x37993871,0x38c53934,0x34d8363f,0x37af3851,0x2fb032cc,
0x3bf43bff,0x3beb3bfe,0x3bbf3bdf,0x3b8c3bc5,0x3b613b95,0x3ae53b41,0x3adc3b23,0x39fd3a79,0x3a323a8b,0x38dc3973,0x396739d1,0x37183839,0x388038f7,0x343535ae,0x37023803,0x2ca93166,
0x3be93bfd,0x3bdd3bfc,0x3b853bc1,0x3b413b9e,0x3ad43b35,0x3a343ac8,0x39de3a61,0x38c53988,0x38ac394b,0x361737e0,0x36963800,0x30863435,0x3322351a,0xaecf2484,0x267b2ffb,0xb590b352,
0x3be83bfd,0x3bdb3bfc,0x3b7d3bbd,0x3b383b99,0x3ac13b29,0x3a1e3ab9,0x39bd3a48,0x389f396a,0x387b3923,0x35a83783,0x3611378e,0x2ecf336b,0x31d53484,0xb0b8a54d,0xa5b22d26,0xb645b45a,
0x3be63bfd,0x3bd93bfc,0x3b753bb9,0x3b2e3b94,0x3aaf3b1c,0x3a083aa9,0x399c3a2e,0x3878394b,0x384938fa,0x35373724,0x358a3718,0x2c903269,0x308633d9,0xb207ab8e,0xac77289d,0xb6f6b508,
0x3be53bfd,0x3bd73bfb,0x3b6d3bb5,0x3b253b8f,0x3a9b3b0f,0x39f13a9a,0x397a3a14,0x3851392d,0x381638cf,0x34c636c3,0x350236a1,0x289d3166,0x2e6b32a7,0xb352ae39,0xaf7ea052,0xb7a4b5b3,
0x3be33bfd,0x3bd53bfb,0x3b653bb0,0x3b1b3b8a,0x3a883b01,0x39d93a8a,0x395739f9,0x3829390d,0x37c538a4,0x34543662,0x34783628,0x12483061,0x2b8e3172,0xb44eb055,0xb141aac5,0xb826b65c,
0x3be23bfd,0x3bd33bfb,0x3b5c3bac,0x3b103b85,0x3a733af4,0x39c13a79,0x393439de,0x380038ed,0x375c3878,0x33c035ff,0x33d935ae,0xa86b2eb6,0x2484303c,0xb4f0b18b,0xb2bfae39,0xb878b702,
0x3be03bfc,0x3bd13bfb,0x3b533ba7,0x3b063b7f,0x3a5f3ae5,0x39a93a68,0x391039c1,0x37af38cd,0x36f1384c,0x32d8359c,0x32bf3531,0xac772ca9,0xa6162e07,0xb590b2bf,0xb41db086,0xb8c8b7a4,
0x3bde3bfc,0x3bcf3bfb,0x3b4b3ba3,0x3afb3b7a,0x3a4a3ad7,0x39913a57,0x38eb39a5,0x375c38ac,0x3684381e,0x31ee3537,0x31a434b4,0xaeb62934,0xac2b2b2a,0xb62eb3f1,0xb4d8b1ee,0xb914b821,
0x3bcd3bfa,0x3bbb3bf8,0x3af03b74,0x3a933b43,0x39783a46,0x38a239b0,0x3707388b,0x344736e0,0x310334d2,0xacdb2e39,0xb07a2052,0xb690b3e5,0xb6c9b490,0xb991b87e,0xb95eb86e,0xbb30ba79,
0x3bcb3bfa,0x3bb93bf8,0x3ae53b6e,0x3a863b3c,0x395e3a34,0x3885399c,0x36b23869,0x33d93696,0x3016346c,0xaeb62c90,0xb197a616,0xb713b472,0xb761b526,0xb9ccb8be,0xb9a5b8b9,0xbb58baad,
0x3bc93bfa,0x3bb63bf8,0x3ada3b68,0x3a793b35,0x39443a22,0x38693988,0x365c3846,0x3322364b,0x2e523405,0xb04829ca,0xb2b3ab2a,0xb793b4f0,0xb7f6b5b9,0xba05b8fc,0xb9e8b901,0xbb7dbadd,
0x3bc73bfa,0x3bb43bf7,0x3acf3b62,0x3a6c3b2e,0x392a3a10,0x384c3973,0x36053824,0x326935ff,0x2c77333a,0xb13424e9,0xb3cdada3,0xb809b56d,0xb844b64b,0xba3cb939,0xba28b947,0xbb9dbb0a,
0x3bc53bf9,0x3bb13bf7,0x3ac33b5c,0x3a5f3b27,0x391039fd,0x382e395e,0x35ae3800,0x31b035b3,0x29343269,0xb21f9f12,0xb472afb0,0xb846b5e8,0xb88bb6da,0xba70b973,0xba65b98a,0xbbb9bb34,
0x3bc23bf9,0x3baf3bf7,0x3ab73b56,0x3a513b20,0x38f539ea,0x38113949,0x355537ba,0x30f63567,0x21e43197,0xb309a839,0xb4fcb0de,0xb883b662,0xb8cfb767,0xbaa1b9ab,0xba9db9ca,0xbbd0bb5a,
0x3bc03bf9,0x3bac3bf7,0x3aab3b50,0x3a443b19,0x38d939d7,0x37e63934,0x34fc3772,0x303c351a,0xa48430c5,0xb3f1ab8e,0xb584b1e2,0xb8beb6da,0xb912b7f1,0xbacfb9e2,0xbad2ba08,0xbbe3bb7c,
0x3bbe3bf9,0x3ba93bf6,0x3a9f3b49,0x3a363b12,0x38be39c4,0x37a9391e,0x34a23729,0x2f0134cc,0xa9fd2fe2,0xb46cad71,0xb60bb2e4,0xb8f7b750,0xb953b83c,0xbafaba16,0xbb03ba42,0xbbf1bb9a,
0x96488000,0xa6ad8000,0x9cb69a48,0xad00aaac,0x9fdb9e48,0xb029aeaa,0xa17fa0b6,0xb1cfb0fd,0xa311a248,0xb371b2a1,0xa452a3db,0xb487b420,0xa51ba4b6,0xb552b4ed,0xa5e4a57f,0xb61ab5b6,
0x9cb68000,0xa7768000,0xa311a0b6,0xad97ab75,0xa5e4a4b6,0xb0a6af72,0xa81fa711,0xb27cb191,0xa94da8b6,0xb426b365,0xaa7aa9e3,0xb50bb499,0xaba7ab11,0xb5ebb57c,0xac6aac1f,0xb6c6b659,
0x9fdb8000,0xa81f8000,0xa5e4a3db,0xae2dac1f,0xa8e8a7da,0xb122b01d,0xaadea9e3,0xb328b226,0xac6aabd9,0xb493b414,0xad65ace7,0xb58db511,0xae5fade2,0xb682b608,0xaf59aedc,0xb76fb6f9,
0xa17f8000,0xa8848000,0xa81fa57f,0xaec3ac83,0xaadea97f,0xb19eb080,0xacceac1f,0xb3d3b2b9,0xae2dad7e,0xb4ffb475,0xaf8baedc,0xb60eb587,0xb074b01d,0xb715b693,0xb122b0cb,0xb80ab796,
0xa3118000,0xa8e88000,0xa94da711,0xaf59ace7,0xac6aab11,0xb219b0e4,0xae2dad4c,0xb43eb34c,0xafefaf0e,0xb56ab4d5,0xb0d7b067,0xb68db5fd,0xb1b6b147,0xb7a6b71b,0xb294b226,0xb85ab817,
0xa4528000,0xa94d8000,0xaa7aa852,0xafefad4c,0xad65ac51,0xb294b147,0xaf8bae78,0xb493b3df,0xb0d7b04e,0xb5d4b534,0xb1e8b160,0xb70ab670,0xb2f7b26f,0xb81ab7a1,0xb402b37d,0xb8a8b862,
0xa51b8000,0xa9b18000,0xaba7a91b,0xb042adb0,0xae5fad1a,0xb30fb1aa,0xb074afa4,0xb4e7b438,0xb1b6b115,0xb63cb593,0xb2f7b257,0xb785b6e3,0xb41ab396,0xb85fb812,0xb4b7b469,0xb8f3b8ab,
0xa5e48000,0xaa168000,0xac6aa9e3,0xb08dae14,0xaf59ade2,0xb389b20d,0xb122b067,0xb53ab481,0xb294b1db,0xb6a4b5f1,0xb402b34c,0xb7feb753,0xb4b7b45d,0xb8a3b852,0xb56ab511,0xb93cb8f1,
0xaa7a8000,0xacce8000,0xb0d7ae78,0xb328b0cb,0xb402b26f,0xb5dfb4bd,0xb58db4c9,0xb805b6f9,0xb70ab64e,0xb902b887,0xb83ab7c2,0xb9e3b976,0xb8e5b891,0xbaa2ba47,0xb982b935,0xbb3abaf3,
0xaade8000,0xad008000,0xb122aedc,0xb371b0fd,0xb43eb2d2,0xb61ab4ed,0xb5dfb511,0xb82ab73d,0xb76fb6aa,0xb92eb8b0,0xb874b817,0xba11b9a4,0xb924b8ce,0xbaceba74,0xb9c5b976,0xbb60bb1d,
0xab438000,0xad338000,0xb16caf40,0xb3bab12e,0xb47bb334,0xb654b51d,0xb631b558,0xb850b780,0xb7d2b705,0xb958b8d8,0xb8adb84d,0xba3db9d0,0xb962b909,0xbaf7baa0,0xba04b9b5,0xbb83bb43,
0xaba78000,0xad658000,0xb1b6afa4,0xb402b160,0xb4b7b396,0xb68db54c,0xb682b59f,0xb874b7c2,0xb81ab75e,0xb982b900,0xb8e5b881,0xba67b9fa,0xb99db943,0xbb1ebac9,0xba41b9f2,0xbba1bb67,
0xac068000,0xad978000,0xb201b004,0xb426b191,0xb4f3b3f7,0xb6c6b57c,0xb6d2b5e5,0xb899b802,0xb84ab7b7,0xb9aab927,0xb91bb8b5,0xba90ba23,0xb9d6b97b,0xbb42baf0,0xba7aba2b,0xbbbcbb86,
0xac388000,0xadc98000,0xb24bb036,0xb44bb1c3,0xb52fb42c,0xb6ffb5ab,0xb721b62b,0xb8bcb822,0xb87ab807,0xb9d2b94d,0xb94fb8e7,0xbab6ba4b,0xba0db9b1,0xbb63bb14,0xbab0ba62,0xbbd2bba2,
0xac6a8000,0xadfb8000,0xb294b067,0xb46fb1f4,0xb56ab45d,0xb737b5da,0xb76fb670,0xb8e0b842,0xb8a8b832,0xb9f8b972,0xb982b918,0xbadbba71,0xba41b9e5,0xbb81bb36,0xbae1ba95,0xbbe3bbbb,
0xac9c8000,0xae2d8000,0xb2deb099,0xb493b226,0xb5a5b48d,0xb76fb608,0xb7bdb6b5,0xb902b862,0xb8d6b85d,0xba1db996,0xb9b3b948,0xbafeba95,0xba73ba17,0xbb9cbb55,0xbb10bac6,0xbbf1bbd0,
0xae5f8000,0xafef8000,0xb4b7b257,0xb5d4b3df,0xb7a6b637,0xb8a8b7a1,0xb924b881,0xba1db96d,0xba41b9ba,0xbb32bab5,0xbb1ebab8,0xbbd6bb93,0xbbb3bb72,0xbbfebbf9,0xbbfabbe1,0xbba9bbe3,
0xae918000,0xb0108000,0xb4dbb288,0xb5f7b408,0xb7ddb665,0xb8c1b7cd,0xb946b8a0,0xba39b989,0xba64b9dc,0xbb4abad0,0xbb3dbad9,0xbbe2bba6,0xbbc8bb8c,0xbbf9bbfe,0xbbffbbee,0xbb8bbbd2,
0xaec38000,0xb0298000,0xb4ffb2b9,0xb61ab420,0xb80ab693,0xb8dbb7f9,0xb966b8bf,0xba54b9a4,0xba85b9fe,0xbb60bae9,0xbb59baf9,0xbbedbbb7,0xbbd9bba4,0xbbf0bc00,0xbc00bbf8,0xbb6abbbe,
0xaef58000,0xb0428000,0xb523b2ea,0xb63cb438,0xb825b6c1,0xb8f3b812,0xb986b8dd,0xba6fb9be,0xbaa5ba1f,0xbb76bb02,0xbb73bb17,0xbbf5bbc7,0xbbe7bbb9,0xbbe4bbff,0xbbfcbbfe,0xbb45bba6,
0xaf278000,0xb05b8000,0xb546b31b,0xb65fb451,0xb840b6ee,0xb90cb828,0xb9a6b8fb,0xba89b9d8,0xbac4ba3f,0xbb89bb1a,0xbb8bbb33,0xbbfbbbd5,0xbbf2bbcb,0xbbd6bbfb,0xbbf4bc00,0xbb1bbb8a,
0xaf598000,0xb0748000,0xb56ab34c,0xb682b469,0xb85ab71b,0xb924b83d,0xb9c5b918,0xbaa2b9f2,0xbae1ba5e,0xbb9cbb30,0xbba1bb4e,0xbbffbbe1,0xbbfabbdb,0xbbc3bbf5,0xbbe7bbfe,0xbaeebb6b,
0xaf8b8000,0xb08d8000,0xb58db37d,0xb6a4b481,0xb874b748,0xb93cb852,0xb9e3b935,0xbababa0b,0xbafeba7c,0xbbacbb46,0xbbb5bb67,0xbc00bbeb,0xbbffbbe8,0xbbaebbec,0xbbd7bbf9,0xbabdbb49,
0xafbd8000,0xb0a68000,0xb5b1b3ae,0xb6c6b499,0xb88eb775,0xb954b867,0xba00b951,0xbad1ba23,0xbb18ba99,0xbbbcbb5a,0xbbc6bb7d,0xbbffbbf3,0xbc00bbf2,0xbb96bbe0,0xbbc2bbf0,0xba89bb22,
0xb0be8000,0xb1858000,0xb6e8b4b1,0xb7f3b570,0xb96bb87c,0xba19b91d,0xbae8ba3b,0xbb7fbae6,0xbbc9bb6e,0xbc00bbdd,0xbbfcbbf9,0xbb8ebbe5,0xbb7abbd1,0xba35bafc,0xba50baf9,0xb820b93e,
0xb0d78000,0xb19e8000,0xb70ab4c9,0xb80ab587,0xb982b891,0xba2db930,0xbafeba52,0xbb8ebaf9,0xbbd6bb80,0xbc00bbe6,0xbbf6bbfd,0xbb76bbda,0xbb5cbbc0,0xba00bad6,0xba15bacc,0xb79bb8fb,
0xb0f08000,0xb1b68000,0xb72cb4e1,0xb81ab59f,0xb999b8a6,0xba41b943,0xbb13ba69,0xbb9cbb0b,0xbbe0bb91,0xbbfebbed,0xbbeebc00,0xbb5cbbcd,0xbb3abbab,0xb9c9baae,0xb9d6ba9c,0xb6f4b8b5,
0xb1098000,0xb1cf8000,0xb74eb4f9,0xb82ab5b6,0xb9afb8ba,0xba54b956,0xbb27ba7f,0xbba9bb1d,0xbbe9bba0,0xbbfbbbf4,0xbbe3bc00,0xbb3fbbbe,0xbb16bb95,0xb990ba83,0xb994ba69,0xb648b86d,
0xb1228000,0xb1e88000,0xb76fb511,0xb83ab5ce,0xb9c5b8ce,0xba67b969,0xbb3aba95,0xbbb5bb2e,0xbbf1bbaf,0xbbf6bbf8,0xbbd7bbfe,0xbb21bbad,0xbaeebb7b,0xb954ba56,0xb94fba33,0xb599b822,
0xb13b8000,0xb2018000,0xb790b529,0xb84ab5e5,0xb9dab8e2,0xba7ab97b,0xbb4cbaaa,0xbbc0bb3e,0xbbf7bbbc,0xbbefbbfc,0xbbc8bbfb,0xbb01bb9b,0xbac4bb5f,0xb916ba27,0xb907b9fa,0xb4e7b7ac,
0xb1538000,0xb2198000,0xb7b2b540,0xb85ab5fd,0xb9f0b8f6,0xba8cb98d,0xbb5ebabf,0xbbcbbb4e,0xbbfcbbc9,0xbbe7bbff,0xbbb7bbf6,0xbadebb86,0xba97bb41,0xb8d6b9f6,0xb8bcb9be,0xb432b710,
0xb16c8000,0xb2328000,0xb7d2b558,0xb86ab614,0xba04b909,0xba9eb99f,0xbb6fbad3,0xbbd4bb5d,0xbbfebbd4,0xbbdebc00,0xbba3bbee,0xbababb70,0xba67bb20,0xb894b9c3,0xb86fb980,0xb2f7b670,
0x98b69248,0xa901a2ad,0x9d7f9bdb,0xadd5ac2b,0xa0529f12,0xb093af7e,0xa1e4a11b,0xb238b166,0xa376a2ad,0xb3d9b309,0xa484a420,0xb4bab454,0xa54da4e9,0xb584b520,0xa616a5b2,0xb64bb5e8,
0x9f1298b6,0xa998a376,0xa420a1e4,0xae84aca9,0xa67ba54d,0xb11cb02f,0xa86ba7a8,0xb2f0b207,0xa998a901,0xb460b3d9,0xaac5aa2f,0xb543b4d2,0xabf2ab5c,0xb622b5b3,0xac90ac44,0xb6fcb690,
0xa1e49bdb,0xaa2fa420,0xa6dfa4e9,0xaf33ad26,0xa966a86b,0xb1a4b09f,0xab5caa61,0xb3a8b2a7,0xaca9ac2b,0xb4d2b454,0xada3ad26,0xb5cbb54f,0xae9dae20,0xb6beb645,0xaf97af1a,0xb7a9b734,
0xa4209d7f,0xaac5a484,0xa8cfa6df,0xafe2ada3,0xab8eaa2f,0xb22cb10f,0xad26ac77,0xb42fb346,0xae84add5,0xb543b4ba,0xafe2af33,0xb651b5cb,0xb09fb048,0xb756b6d4,0xb14db0f6,0xb829b7d5,
0xa54d9f12,0xab5ca4e9,0xaa2fa86b,0xb048ae20,0xacdbabf2,0xb2b3b17f,0xae9dadbc,0xb48ab3e5,0xb02faf7e,0xb5b3b520,0xb10fb09f,0xb6d4b645,0xb1eeb17f,0xb7ebb761,0xb2ccb25d,0xb87bb839,
0xa67ba052,0xabf2a54d,0xab8ea966,0xb09fae9d,0xadeeacdb,0xb33ab1ee,0xb00aaf01,0xb4e4b441,0xb11cb093,0xb622b584,0xb22cb1a4,0xb756b6be,0xb33ab2b3,0xb83eb7eb,0xb423b3c0,0xb8cab885,
0xa7a8a11b,0xac44a5b2,0xac77aa61,0xb0f6af1a,0xaf01adbc,0xb3c0b25d,0xb0c5b023,0xb53db490,0xb207b166,0xb690b5e8,0xb346b2a7,0xb7d5b734,0xb441b3e5,0xb885b839,0xb4deb490,0xb917b8cf,
0xa86ba1e4,0xac90a616,0xad26ab5c,0xb14daf97,0xb00aae9d,0xb423b2cc,0xb17fb0c5,0xb596b4de,0xb2f0b238,0xb6fcb64b,0xb42fb3a8,0xb829b7a9,0xb4e4b48a,0xb8cab87b,0xb596b53d,0xb961b917,
0xacdba67b,0xaf33a8cf,0xb1a4b00a,0xb429b1fa,0xb466b33a,0xb66db54f,0xb5eeb52c,0xb846b783,0xb767b6ad,0xb93db8c5,0xb866b80e,0xba16b9ae,0xb90db8bb,0xbacbba75,0xb9a7b95c,0xbb5abb18,
0xad26a6df,0xaf7ea901,0xb1fab048,0xb454b238,0xb4a8b3a8,0xb6adb584,0xb645b579,0xb86eb7ca,0xb7d0b70d,0xb96ab8f0,0xb8a2b846,0xba44b9db,0xb94eb8fa,0xbaf7baa2,0xb9eab99e,0xbb7ebb40,
0xad71a744,0xafc9a934,0xb251b086,0xb47eb276,0xb4eab40b,0xb6ebb5b9,0xb69bb5c5,0xb895b809,0xb81cb76c,0xb995b919,0xb8dcb87e,0xba70ba08,0xb98cb936,0xbb1fbacd,0xba2ab9de,0xbb9ebb65,
0xadbca7a8,0xb00aa966,0xb2a7b0c5,0xb4a8b2b3,0xb52cb441,0xb729b5ee,0xb6f1b611,0xb8bbb82c,0xb84eb7ca,0xb9bfb942,0xb914b8b4,0xba9aba32,0xb9c8b971,0xbb44baf5,0xba66ba1a,0xbbbabb86,
0xae07a806,0xb02fa998,0xb2fdb103,0xb4d2b2f0,0xb56db478,0xb767b622,0xb745b65c,0xb8e1b84e,0xb880b813,0xb9e8b96a,0xb94bb8e8,0xbac1ba5b,0xba01b9a9,0xbb66bb1b,0xba9fba53,0xbbd1bba3,
0xae52a839,0xb055a9ca,0xb352b141,0xb4fcb32e,0xb5aeb4ae,0xb7a4b656,0xb799b6a7,0xb906b871,0xb8b1b841,0xba10b991,0xb981b91c,0xbae7ba82,0xba38b9e0,0xbb85bb3d,0xbad4ba8a,0xbbe3bbbc,
0xae9da86b,0xb07aa9fd,0xb3a8b17f,0xb526b36b,0xb5eeb4e4,0xb7e0b68a,0xb7ebb6f1,0xb92ab892,0xb8e1b86e,0xba36b9b7,0xb9b4b94e,0xbb0abaa8,0xba6cba14,0xbba0bb5d,0xbb04babc,0xbbf1bbd1,
0xaee8a89d,0xb09faa2f,0xb3fdb1bd,0xb54fb3a8,0xb62eb51a,0xb80eb6be,0xb81eb73a,0xb94eb8b4,0xb910b89a,0xba5bb9db,0xb9e6b97e,0xbb2cbacb,0xba9dba46,0xbbb8bb7b,0xbb31baec,0xbbfbbbe3,
0xb0c5aa61,0xb1eeabf2,0xb579b3e5,0xb6beb4e4,0xb82cb6f1,0xb90db83e,0xb971b8d4,0xba6cb9c8,0xba7fb9ff,0xbb66baf7,0xbb4bbaed,0xbbebbbb8,0xbbcdbb95,0xbbf4bc00,0xbbffbbf0,0xbb80bbca,
0xb0eaaa93,0xb213ac12,0xb5a2b411,0xb6e5b502,0xb849b724,0xb928b856,0xb993b8f5,0xba88b9e4,0xbaa1ba22,0xbb7cbb10,0xbb67bb0d,0xbbf4bbc8,0xbbdebbad,0xbbeabc00,0xbbffbbf9,0xbb5cbbb3,
0xb10faac5,0xb238ac2b,0xb5cbb42f,0xb70db520,0xb866b756,0xb942b86e,0xb9b4b914,0xbaa2b9ff,0xbac1ba44,0xbb90bb29,0xbb81bb2c,0xbbfbbbd6,0xbbebbbc1,0xbbdbbbfc,0xbbfbbbff,0xbb34bb98,
0xb134aaf8,0xb25dac44,0xb5f4b44e,0xb734b53d,0xb883b788,0xb95cb885,0xb9d5b934,0xbabcba1a,0xbae1ba65,0xbba3bb40,0xbb99bb48,0xbbffbbe3,0xbbf6bbd3,0xbbcabbf6,0xbbf2bc00,0xbb07bb7a,
0xb15aab2a,0xb282ac5e,0xb61db46c,0xb75cb55b,0xb89fb7ba,0xb975b89d,0xb9f5b953,0xbad5ba34,0xbafeba84,0xbbb4bb56,0xbbafbb62,0xbc00bbed,0xbbfcbbe2,0xbbb5bbed,0xbbe4bbfd,0xbad7bb57,
0xb17fab5c,0xb2a7ac77,0xb645b48a,0xb783b579,0xb8bbb7eb,0xb98eb8b4,0xba14b971,0xbaedba4e,0xbb1bbaa2,0xbbc3bb6b,0xbbc1bb7b,0xbbffbbf5,0xbc00bbee,0xbb9cbbe1,0xbbd2bbf6,0xbaa2bb31,
0xb1a4ab8e,0xb2ccac90,0xb66db4a8,0xb7a9b596,0xb8d7b80e,0xb9a7b8ca,0xba32b98e,0xbb04ba66,0xbb35bac0,0xbbd1bb7e,0xbbd2bb91,0xbbfbbbfb,0xbbffbbf7,0xbb80bbd2,0xbbbbbbeb,0xba6abb07,
0xb1c9abc0,0xb2f0aca9,0xb696b4c6,0xb7d0b5b3,0xb8f2b826,0xb9bfb8e1,0xba4fb9ab,0xbb1bba7f,0xbb4ebadc,0xbbddbb90,0xbbe0bba6,0xbbf5bbfe,0xbbfcbbfd,0xbb61bbc0,0xbba0bbdd,0xba2ebada,
0xb315acc2,0xb41dad8a,0xb7f6b5d1,0xb890b6b8,0xb9d7b8f7,0xba86b9a0,0xbb30ba96,0xbbb5bb39,0xbbe7bba1,0xbbfabbf6,0xbbecbc00,0xbb4cbbc1,0xbb3fbbab,0xb9bfba9f,0xb9efbaa9,0xb707b8b4,
0xb33aacdb,0xb42fada3,0xb80eb5ee,0xb8a2b6d4,0xb9efb90d,0xba9ab9b4,0xbb44baad,0xbbc1bb4b,0xbbefbbb0,0xbbf5bbfb,0xbbe0bbff,0xbb2dbbaf,0xbb19bb93,0xb983ba72,0xb9abba75,0xb656b869,
0xb35facf4,0xb441adbc,0xb821b60b,0xb8b4b6f1,0xba05b923,0xbaadb9c8,0xbb57bac3,0xbbcdbb5b,0xbbf6bbbe,0xbbeebbfe,0xbbd3bbfd,0xbb0cbb9c,0xbaf0bb78,0xb944ba42,0xb965ba3e,0xb5a2b81c,
0xb383ad0d,0xb454add5,0xb834b628,0xb8c5b70d,0xba1cb939,0xbac0b9db,0xbb69bad9,0xbbd6bb6b,0xbbfbbbcb,0xbbe5bc00,0xbbc2bbf8,0xbae9bb87,0xbac5bb5b,0xb903ba10,0xb91cba03,0xb4eab799,
0xb3a8ad26,0xb466adee,0xb846b645,0xb8d7b729,0xba32b94e,0xbad2b9ef,0xbb7bbaed,0xbbdfbb7a,0xbbfebbd6,0xbbdabc00,0xbbafbbf1,0xbac3bb6f,0xba96bb3b,0xb8c0b9db,0xb8cfb9c6,0xb42fb6f6,
0xb3cdad3f,0xb478ae07,0xb859b662,0xb8e8b745,0xba48b963,0xbae4ba01,0xbb8bbb01,0xbbe7bb88,0xbc00bbe0,0xbbcebbff,0xbb9abbe8,0xba9bbb56,0xba65bb18,0xb87bb9a5,0xb880b985,0xb2e4b651,
0xb3f1ad58,0xb48aae20,0xb86bb67f,0xb8fab761,0xba5db978,0xbaf5ba14,0xbb9abb15,0xbbeebb95,0xbc00bbe9,0xbbc0bbfc,0xbb82bbdd,0xba72bb3b,0xba30baf2,0xb834b96c,0xb82eb942,0xb166b5a8,
0xb40bad71,0xb49cae39,0xb87eb69b,0xb90bb77d,0xba72b98c,0xbb06ba26,0xbba8bb27,0xbbf4bba2,0xbbfebbf0,0xbbb0bbf9,0xbb68bbd0,0xba46bb1d,0xb9f9baca,0xb7d5b931,0xb7b4b8fc,0xafc9b4fc,
0x39b839ba,0x3a973ab5,0x39b339b5,0x3a583a78,0x39af39b1,0x3a153a37,0x39aa39ad,0x39cd39f2,0x39a639a8,0x398239a8,0x39a139a4,0x3933395b,0x399d399f,0x38e03909,0x3999399b,0x388938b5,
0xb979b972,0xb865b832,0xb986b980,0xb8c7b896,0xb994b98d,0xb924b8f6,0xb9a1b99b,0xb97db951,0xb9afb9a8,0xb9d2b9a8,0xb9bcb9b5,0xba21b9fa,0xb9c9b9c3,0xba6bba47,0xb9d6b9d0,0xbab0ba8e,
0xb9f4b9fe,0xbac7bae9,0xb9dfb9e9,0xba7ebaa3,0xb9c9b9d4,0xba2dba56,0xb9b3b9be,0xb9d6ba02,0xb99db9a8,0xb979b9a8,0xb986b992,0xb916b948,0xb970b97b,0xb8adb8e2,0xb958b964,0xb840b877,
0x39373927,0x381a37b7,0x39583948,0x38943858,0x39793969,0x390738ce,0x39993989,0x3974393e,0x39b839a8,0x39da39a8,0x39d639c7,0x3a393a0b,0x39f439e5,0x3a903a65,0x3a113a02,0x3ade3ab8,
0x3a2d3a3f,0x3af43b1a,0x3a093a1b,0x3aa23acc,0x39e339f6,0x3a453a74,0x39bc39d0,0x39df3a13,0x399439a8,0x397039a8,0x396b3980,0x38f83935,0x39413956,0x387a38ba,0x3916392b,0x37e83838,
0xb8f3b8d8,0xb79bb705,0xb929b90e,0xb85fb817,0xb95db943,0xb8eab8a6,0xb990b976,0xb96bb92b,0xb9c0b9a8,0xb9e3b9a8,0xb9f0b9d8,0xba50ba1b,0xba1dba07,0xbab3ba83,0xba49ba33,0xbb0abae0,
0xba64ba7c,0xbb1ebb46,0xba31ba4b,0xbac4baf3,0xb9fcba17,0xba5cba92,0xb9c5b9e1,0xb9e7ba23,0xb98bb9a8,0xb966b9a8,0xb94fb96d,0xb8dbb922,0xb911b930,0xb845b891,0xb8d1b8f1,0xb74eb7ee,
0x38ad3887,0x36ff364e,0x38f838d3,0x382a37ac,0x3941391d,0x38cc387c,0x39863964,0x39623918,0x39c939a8,0x39eb39a8,0x3a0939e9,0x3a673a2b,0x3a453a27,0x3ad53aa0,0x3a7e3a62,0x3b323b05,
0x3b453b6e,0x3bbc3bdd,0x3ae53b17,0x3b573b8f,0x3a733aae,0x3ac73b14,0x39f03a33,0x3a113a71,0x395d39a8,0x393739a8,0x38bc390e,0x384038bf,0x380f3867,0x365f3775,0x36af376a,0x341a3540,
0xb65fb593,0xb389b115,0xb7e8b726,0xb625b4f9,0xb8adb852,0xb830b748,0xb958b905,0xb933b8b5,0xb9f4b9a8,0xba15b9a8,0xba7eba3b,0xbad1ba78,0xbaf4babc,0xbb63bb20,0xbb57bb28,0xbbc6bb9b,
0xbb68bb91,0xbbd0bbed,0xbb04bb39,0xbb6fbba6,0xba89bac9,0xbadbbb2b,0xb9f8ba43,0xba19ba7f,0xb954b9a8,0xb92eb9a8,0xb89eb8fb,0xb820b8ab,0xb7b2b83d,0xb5ebb71b,0xb60eb6e3,0xb2deb4b1,
0x35bc34d5,0x32322f0e,0x377a369e,0x35b13469,0x388e3828,0x380f36ee,0x394f38f1,0x392938a0,0x39fc39a8,0x3a1d39a8,0x3a933a4b,0x3ae53a87,0x3b133ad6,0x3b7a3b36,0x3b783b49,0x3bd93bb1,
0x3b873baf,0x3be13bf8,0x3b213b58,0x3b853bbb,0x3a9e3ae3,0x3aee3b41,0x3a003a52,0x3a213a8e,0x394a39a8,0x392439a8,0x387f38e7,0x37fe3896,0x37423812,0x357636c1,0x356a3659,0x31853420,
0xb517b414,0xb0d7abd9,0xb70ab614,0xb53ab3ae,0xb86fb7f9,0xb7ddb693,0xb946b8dd,0xb91fb88c,0xba04b9a8,0xba25b9a8,0xbaa9ba5a,0xbaf7ba95,0xbb2fbaf0,0xbb90bb4b,0xbb96bb67,0xbbe8bbc4,
0xbba3bbc9,0xbbefbbff,0xbb3dbb74,0xbb9abbcd,0xbab3bafc,0xbb01bb55,0xba09ba62,0xba29ba9c,0xb941b9a8,0xb91bb9a8,0xb85fb8d3,0xb7bdb881,0xb6d2b7cd,0xb4ffb665,0xb4c3b5ce,0xb029b31b,
0x346f32a1,0x2ef52248,0x36993587,0x34c33288,0x385037a1,0x379b3637,0x393c38c9,0x39163877,0x3a0d39a8,0x3a2d39a8,0x3abd3a69,0x3b0a3aa3,0x3b4a3b08,0x3ba33b5f,0x3bb03b82,0x3bf43bd5,
0x3bf83c00,0x3bf93bd4,0x3bac3bdc,0x3be43bfe,0x3b133b69,0x3b543bab,0x3a313aaa,0x3a503ae0,0x391139a8,0x38ea39a8,0x377a386d,0x366b3817,0x34873608,0x313b348d,0x2d9731f4,0xad65291b,
0xac3828b6,0x2ec33365,0xb44bb160,0xb0bea57f,0xb759b5da,0xb648b45d,0xb90cb862,0xb8e5b80d,0xba35b9a8,0xba54b9a8,0xbb1bbab1,0xbb5cbae6,0xbbb5bb72,0xbbe9bbb2,0xbbfcbbe3,0xbbf5bc00,
0xbbfebbfc,0xbbefbbbc,0xbbbdbbe9,0xbbeebc00,0xbb24bb7b,0xbb63bbb9,0xba39bab8,0xba58baed,0xb907b9a8,0xb8e0b9a8,0xb737b858,0xb625b802,0xb40eb5ab,0xb042b42c,0xa9b1b0cb,0x30109a48,
0x25e4ad7e,0xb0beb475,0x33a23036,0x2f8ba3db,0x3715357c,0x360233f7,0x3902384d,0x38db37ee,0x3a3d39a8,0x3a5c39a8,0x3b2c3abf,0x3b6a3af3,0x3bc53b84,0x3bf23bc0,0x3bff3bee,0x3be93c00,
0x3c003bf4,0x3be23ba0,0x3bcc3bf3,0x3bf53bff,0x3b353b8c,0x3b713bc6,0x3a413ac6,0x3a603af9,0x38fd39a8,0x38d639a8,0x36f43842,0x35df37d8,0x3328354c,0x2e913396,0x16482f40,0xb16ca852,
0x251b304e,0x32193534,0xb2adae14,0xad972aac,0xb6d2b51d,0xb5bcb334,0xb8f8b838,0xb8d1b7c2,0xba45b9a8,0xba64b9a8,0xbb3dbacc,0xbb78baff,0xbbd3bb95,0xbbf8bbcb,0xbc00bbf7,0xbbdabbfd,
0xbbfebbe6,0xbbd2bb80,0xbbd9bbfa,0xbbfbbbfb,0xbb45bb9d,0xbb7fbbd1,0xba49bad3,0xba67bb05,0xb8f3b9a8,0xb8ccb9a8,0xb6afb82d,0xb599b7ac,0xb232b4ed,0xac9cb2d2,0x294dace7,0x32c62c83,
0xac06b1db,0xb371b5f1,0x31b62b75,0x2b43adb0,0x368d34bd,0x3576326f,0x38ee3822,0x38c73796,0x3a4d39a8,0x3a6b39a8,0x3b4c3ad9,0x3b853b0b,0x3bdf3ba4,0x3bfd3bd6,0x3bfc3bfd,0x3bc83bf8,
0x3bbd3b5a,0x3b473a99,0x3bfe3bf4,0x3bf93bbe,0x3b8b3bdb,0x3bb83bf7,0x3a6f3b11,0x3a8c3b3e,0x38c139a8,0x389939a8,0x35523780,0x343236cc,0x294d320d,0xad332de2,0xb40eaedc,0xb6a4b408,
0x346336aa,0x36f438b0,0xa6ad3004,0x2e2d3451,0xb52fb1aa,0xb40ead1a,0xb8bcb76a,0xb894b6b5,0xba73b9a8,0xba90b9a8,0xbb92bb17,0xbbbdbb43,0xbbffbbe0,0xbbf6bbf9,0xbbb2bbf0,0xbb35bbb4,
0xbba5bb30,0xbb21ba5e,0xbc00bbeb,0xbbf3bbaa,0xbb98bbe4,0xbbc2bbfb,0xba76bb1d,0xba93bb49,0xb8b7b9a8,0xb88eb9a8,0xb50bb753,0xb3d3b69e,0xa17fb147,0x2f27ac51,0x34b73099,0x37423499,
0xb50bb75e,0xb790b900,0x9cb6b12e,0xb010b4e1,0x34e730e4,0x33892b11,0x38b2373d,0x38893687,0x3a7a39a8,0x3a9739a8,0x3b9e3b22,0x3bc63b4e,0x3c003be8,0x3bef3bfd,0x3b983be5,0x3b0d3b9e,
0x3b893b02,0x3af73a1f,0x3c003bdf,0x3beb3b93,0x3ba33bec,0x3bcb3bfe,0x3a7e3b28,0x3a9b3b53,0x38ad39a8,0x388439a8,0x34c33726,0x33403670,0xa51b3080,0xb08d297f,0xb55eb1c3,0xb7ddb529,
0x35b13807,0x3815394d,0x28843257,0x31093570,0xb49fb01d,0xb2f7a7da,0xb8a8b710,0xb87fb659,0xba81b9a8,0xba9eb9a8,0xbba9bb2e,0xbbcfbb58,0xbbffbbef,0xbbe6bbff,0xbb7abbd7,0xbae1bb86,
0xbb6abad0,0xbacbb9dc,0xbbfdbbd0,0xbbe1bb79,0xbbaebbf2,0xbbd3bc00,0xba85bb33,0xbaa2bb5d,0xb8a3b9a8,0xb87ab9a8,0xb47bb6f9,0xb2adb642,0x2a7aaf72,0x3185a4b6,0x360232ea,0x383a35b6,
0xb654b85d,0xb85fb996,0xac38b37d,0xb201b5fd,0x34572eaa,0x32631e48,0x389e36e3,0x3874362b,0x3a8939a8,0x3aa539a8,0x3bb33b39,0x3bd73b62,0x3bfc3bf5,0x3bdc3c00,0x3b593bc7,0x3ab33b6b,
0x39b739b9,0x3a883aa6,0x39b239b4,0x3a483a68,0x39ae39b0,0x3a033a26,0x39a939ab,0x39bb39e0,0x39a539a7,0x396e3995,0x39a039a3,0x391e3947,0x399c399e,0x38ca38f5,0x3997399a,0x3873389f,
0xb97cb975,0xb87eb84c,0xb98ab983,0xb8deb8ae,0xb997b991,0xb93bb90d,0xb9a5b99e,0xb993b967,0xb9b2b9ab,0xb9e6b9bd,0xb9bfb9b9,0xba34ba0e,0xb9ccb9c6,0xba7dba59,0xb9d9b9d3,0xbac0ba9f,
0xb9efb9f9,0xbab6bad9,0xb9d9b9e4,0xba6aba91,0xb9c4b9cf,0xba18ba42,0xb9aeb9b9,0xb9bfb9ec,0xb997b9a3,0xb961b991,0xb981b98c,0xb8fcb92f,0xb96ab975,0xb892b8c8,0xb953b95e,0xb824b85c,
0x3940392f,0x383937f6,0x39613950,0x38b13876,0x39813971,0x392338eb,0x39a03991,0x398e395a,0x39bf39b0,0x39f339c1,0x39de39cf,0x3a4f3a22,0x39fb39ec,0x3aa43a7b,0x3a183a0a,0x3af03acb,
0x3a243a36,0x3ae13b07,0x39ff3a12,0x3a8b3ab7,0x39d939ec,0x3a2c3a5d,0x39b239c6,0x39c439f9,0x398a399e,0x3953398c,0x39613975,0x38d93917,0x3936394b,0x3859389a,0x390b3921,0x37a43816,
0xb901b8e6,0xb7e6b750,0xb936b91c,0xb883b83c,0xb96ab950,0xb90bb8c8,0xb99cb983,0xb98ab94b,0xb9ccb9b4,0xb9ffb9c6,0xb9fbb9e4,0xba6aba36,0xba28ba12,0xbacaba9b,0xba53ba3e,0xbb1dbaf5,
0xba57ba70,0xbb09bb33,0xba24ba3e,0xbaabbadc,0xb9efba0a,0xba40ba77,0xb9b7b9d3,0xb9c8ba05,0xb97cb99a,0xb944b988,0xb940b95e,0xb8b6b8fe,0xb901b921,0xb81eb86b,0xb8c0b8e1,0xb6fcb79e,
0x38c0389a,0x375636a7,0x390b38e6,0x38543800,0x3953392f,0x38f238a4,0x39973975,0x3985393d,0x39d939b9,0x3a0c39ca,0x3a1839f9,0x3a843a4a,0x3a533a36,0x3aed3abb,0x3a8b3a70,0x3b473b1c,
0x3b2e3b5a,0x3ba63bce,0x3aca3afe,0x3b373b74,0x3a533a91,0x3a9d3aef,0x39cc3a12,0x39de3a42,0x39363983,0x38fc3971,0x389238e6,0x37fb3880,0x37c5383c,0x35d136eb,0x3651370d,0x330934ae,
0xb6c3b5fa,0xb460b251,0xb824b788,0xb6b8b590,0xb8d9b880,0xb873b7d5,0xb981b92f,0xb96eb8f5,0xba18b9cf,0xba48b9e0,0xba9dba5d,0xbafabaa6,0xbb0fbad9,0xbb80bb43,0xbb6cbb40,0xbbd8bbb2,
0xbb51bb7d,0xbbbdbbe0,0xbae7bb1f,0xbb4ebb8c,0xba66baa9,0xbaafbb04,0xb9d1ba1e,0xb9e2ba4e,0xb928b97e,0xb8edb96c,0xb86eb8cd,0xb7afb866,0xb74bb80b,0xb54fb684,0xb5a2b679,0xb197b411,
0x362e3549,0x338330de,0x37e6370d,0x3651350e,0x38c0385c,0x38593788,0x397c3921,0x396a38e6,0x3a2439d3,0x3a5339e4,0x3ab63a70,0x3b0f3ab7,0x3b2e3af5,0x3b973b5a,0x3b8d3b61,0x3be83bc7,
0x3b703b9c,0x3bd03bef,0x3b033b3d,0x3b653ba2,0x3a793ac1,0x3ac03b19,0x39d53a2a,0x39e63a59,0x3919397a,0x38de3967,0x384938b4,0x3761384c,0x36cf37b4,0x34cc361d,0x34f035e2,0x302332e4,
0xb596b496,0xb244aecf,0xb783b690,0xb5e8b48a,0xb8a7b836,0xb83eb73a,0xb978b912,0xb965b8d7,0xba30b9d7,0xba5fb9e8,0xbacdba82,0xbb23bac8,0xbb4cbb10,0xbbacbb6f,0xbbaabb7f,0xbbf4bbd8,
0xbb8dbbb7,0xbbe0bbf9,0xbb1dbb5a,0xbb7abbb5,0xba8bbad9,0xbad0bb2d,0xb9d9ba36,0xb9eaba65,0xb90bb975,0xb8cfb963,0xb824b89a,0xb713b831,0xb651b750,0xb447b5b3,0xb43bb549,0xad58b1a4,
0x34fc33c0,0x31032bc0,0x371e3611,0x357e3405,0x388d3811,0x382436eb,0x39733903,0x396138c8,0x3a3c39db,0x3a6a39ec,0x3ae43a94,0x3b373ad9,0x3b673b2a,0x3bbe3b83,0x3bc33b9a,0x3bfc3be7,
0x3bed3bff,0x3bff3bea,0x3b8d3bc7,0x3bcc3bf5,0x3ae13b40,0x3b1d3b83,0x39ef3a70,0x39ff3a9b,0x38c0395e,0x3883394b,0x36c33816,0x357e3750,0x33833549,0x2e84332e,0x28cf3061,0xb0aca5b2,
0xaf7ea376,0x29663166,0xb514b2fd,0xb2bfad71,0xb809b69b,0xb734b555,0xb95cb8b9,0xb949b87b,0xba75b9f1,0xbaa1ba01,0xbb49bae9,0xbb8bbb25,0xbbcfbb96,0xbbf9bbd2,0xbc00bbf2,0xbbe3bbfe,
0xbbf6bc00,0xbbfcbbda,0xbb9fbbd6,0xbbd8bbfb,0xbaf0bb52,0xbb2cbb92,0xb9f3ba7b,0xba03baa6,0xb8b1b95a,0xb873b947,0xb673b7f6,0xb52cb718,0xb276b4de,0xac5eb251,0x2052ae39,0x321f2bf2,
0x2cf4a806,0xad3fb2d8,0x34a831ee,0x31e22a93,0x37db364b,0x36fc3502,0x395738a9,0x3944386b,0x3a8039f5,0x3aab3a05,0x3b5b3af8,0x3b993b33,0x3bdd3ba7,0x3bfd3bdd,0x3bff3bfa,0x3bd13bf9,
0x3bfd3bfd,0x3bf53bc6,0x3baf3be3,0x3be23bff,0x3b003b64,0x3b393ba0,0x39f73a86,0x3a083ab0,0x38a23955,0x38633942,0x362237bf,0x34d836e0,0x31663472,0x286b3172,0xaaf82b5c,0xb390ae84,
0xa8cf2cf4,0x2fc93423,0xb43bb0de,0xb103a484,0xb7a4b5fa,0xb6c3b4ae,0xb953b89a,0xb940b85c,0xba8bb9f9,0xbab6ba0a,0xbb6cbb07,0xbba6bb40,0xbbe8bbb7,0xbc00bbe7,0xbbfabbff,0xbbbabbf1,
0xbc00bbf6,0xbbebbbae,0xbbbebbed,0xbbebbc00,0xbb0fbb74,0xbb47bbad,0xb9fbba91,0xba0cbabb,0xb892b950,0xb854b93d,0xb5d1b788,0xb484b6a7,0xb055b405,0x9248b093,0x2e6ba484,0x347e3086,
0x98b6afe2,0xb128b4d8,0x339c2f97,0x3023a420,0x376c35a8,0x368a345a,0x394e388b,0x393b384c,0x3a9639fd,0x3ac03a0e,0x3b7c3b16,0x3bb33b4d,0x3bf23bc5,0x3c003bef,0x3bf03c00,0x3ba03be5,
0x3bde3b91,0x3b8a3af7,0x3bf23bff,0x3c003be3,0x3b533bb9,0x3b823bdf,0x3a103ac5,0x3a203aec,0x38443939,0x38033925,0x342f366d,0x31b03584,0xa8392f65,0xb15a1d7f,0xb531b1c9,0xb7e0b55b,
0x3269358a,0x35a83819,0xae842a61,0x205231e2,0xb651b405,0xb567b15a,0xb936b83c,0xb923b7f6,0xbacaba12,0xbaf0ba22,0xbbbebb5a,0xbbe3bb88,0xbbfdbbf5,0xbbddbc00,0xbb81bbd6,0xbadfbb7c,
0xbbcebb70,0xbb6dbac6,0xbbf8bbfb,0xbbffbbd6,0xbb60bbc4,0xbb8dbbe7,0xba14bacf,0xba24baf5,0xb834b934,0xb7e6b921,0xb3b4b634,0xb103b549,0x2c44ada3,0x326925b2,0x35e23309,0x384135f4,
0xb3a8b63a,0xb63fb869,0x2cc2ad58,0xa89db2f0,0x3617335f,0x352c30ac,0x3931382c,0x391e37d5,0x3ad43a16,0x3afa3a26,0x3bc93b66,0x3bea3b92,0x3bf93bfa,0x3bcf3bff,0x3b5f3bc5,0x3aad3b5d,
0x3bba3b4c,0x3b4d3a93,0x3bfc3bf6,0x3bfd3bc7,0x3b6c3bce,0x3b973bed,0x3a183ad9,0x3a283afe,0x3824392f,0x37c5391c,0x330935fa,0x3055350e,0xae6b2bc0,0xb377aa61,0xb690b423,0xb890b68a,
0x347236e5,0x36d438b6,0xa9fd2f7e,0x2c1233fd,0xb5dcb2b3,0xb4f0affb,0xb92db81c,0xb919b7b4,0xbaddba1a,0xbb03ba2a,0xbbd3bb72,0xbbf0bb9c,0xbbf2bbfe,0xbbbfbbfc,0xbb38bbaf,0xba77bb3c,
0xbba4bb23,0xbb2aba5b,0xbbffbbee,0xbbfabbb6,0xbb77bbd7,0xbba1bbf3,0xba1cbae2,0xba2cbb07,0xb813b92a,0xb7a4b917,0xb25db5bf,0xaf4cb4d2,0x3048a839,0x34412cf4,0x373a34c0,0x38dc371e,
0xb50eb78e,0xb767b901,0x24e9b0d1,0xadd5b484,0x35a23207,0x34b42e9d,0x3928380b,0x39143793,0x3ae73a1e,0x3b0c3a2e,0x3bdb3b7d,0x3bf53ba6,0x3be93c00,0x3bad3bf7,0x3b0d3b97,0x3a3e3b18,
0xb999b996,0xb889b85d,0xb99db99b,0xb8e0b8b5,0xb9a1b99f,0xb933b909,0xb9a6b9a4,0xb982b95b,0xb9aab9a8,0xb9cdb9a8,0xb9afb9ad,0xba15b9f2,0xb9b3b9b1,0xba58ba37,0xb9b8b9b5,0xba97ba78,
0xb9d6b9dc,0xbab0bad0,0xb9c9b9d0,0xba6bba8e,0xb9bcb9c3,0xba21ba47,0xb9afb9b5,0xb9d2b9fa,0xb9a1b9a8,0xb97db9a8,0xb994b99b,0xb924b951,0xb986b98d,0xb8c7b8f6,0xb979b980,0xb865b896,
0x3958394d,0x38403807,0x39703964,0x38ad3877,0x3986397b,0x391638e2,0x399d3992,0x39793948,0x39b339a8,0x39d639a8,0x39c939be,0x3a2d3a02,0x39df39d4,0x3a7e3a56,0x39f439e9,0x3ac73aa3,
0x3a113a1f,0x3ade3b02,0x39f43a02,0x3a903ab8,0x39d639e5,0x3a393a65,0x39b839c7,0x39da3a0b,0x399939a8,0x397439a8,0x39793989,0x3907393e,0x39583969,0x389438ce,0x39373948,0x381a3858,
0xb916b900,0xb7e8b75e,0xb941b92b,0xb87ab838,0xb96bb956,0xb8f8b8ba,0xb994b980,0xb970b935,0xb9bcb9a8,0xb9dfb9a8,0xb9e3b9d0,0xba45ba13,0xba09b9f6,0xbaa2ba74,0xba2dba1b,0xbaf4bacc,
0xba49ba5e,0xbb0abb30,0xba1dba33,0xbab3bae0,0xb9f0ba07,0xba50ba83,0xb9c0b9d8,0xb9e3ba1b,0xb990b9a8,0xb96bb9a8,0xb95db976,0xb8eab92b,0xb929b943,0xb85fb8a6,0xb8f3b90e,0xb79bb817,
0x38d138b0,0x374e36aa,0x391138f1,0x384537ee,0x394f3930,0x38db3891,0x398b396d,0x39663922,0x39c539a8,0x39e739a8,0x39fc39e1,0x3a5c3a23,0x3a313a17,0x3ac43a92,0x3a643a4b,0x3b1e3af3,
0x3a7e3a99,0x3b323b5a,0x3a453a62,0x3ad53b05,0x3a093a27,0x3a673aa0,0x39c939e9,0x39eb3a2b,0x398639a8,0x396239a8,0x39413964,0x38cc3918,0x38f8391d,0x382a387c,0x38ad38d3,0x36ff37ac,
0xb6afb5f1,0xb41ab1db,0xb80fb76a,0xb65fb540,0xb8bcb867,0xb840b775,0xb95db90e,0xb937b8bf,0xb9f0b9a8,0xba11b9a8,0xba73ba33,0xbac7ba71,0xbae5baae,0xbb57bb14,0xbb45bb17,0xbbbcbb8f,
0xbb57bb80,0xbbc6bbe6,0xbaf4bb28,0xbb63bb9b,0xba7ebabc,0xbad1bb20,0xb9f4ba3b,0xba15ba78,0xb958b9a8,0xb933b9a8,0xb8adb905,0xb830b8b5,0xb7e8b852,0xb625b748,0xb65fb726,0xb389b4f9,
0x360e3534,0x32de304e,0x37b236e3,0x35eb34b1,0x389e383d,0x3820371b,0x395438fb,0x392e38ab,0x39f839a8,0x3a1939a8,0x3a893a43,0x3adb3a7f,0x3b043ac9,0x3b6f3b2b,0x3b683b39,0x3bd03ba6,
0x3b783ba0,0x3bd93bf4,0x3b133b49,0x3b7a3bb1,0x3a933ad6,0x3ae53b36,0x39fc3a4b,0x3a1d3a87,0x394f39a8,0x392939a8,0x388e38f1,0x380f38a0,0x377a3828,0x35b136ee,0x35bc369e,0x32323469,
0xb56ab475,0xb185ad7e,0xb742b659,0xb576b420,0xb87fb812,0xb7feb6c1,0xb94ab8e7,0xb924b896,0xba00b9a8,0xba21b9a8,0xba9eba52,0xbaeeba8e,0xbb21bae3,0xbb85bb41,0xbb87bb58,0xbbe1bbbb,
0xbb96bbbc,0xbbe8bbfc,0xbb2fbb67,0xbb90bbc4,0xbaa9baf0,0xbaf7bb4b,0xba04ba5a,0xba25ba95,0xb946b9a8,0xb91fb9a8,0xb86fb8dd,0xb7ddb88c,0xb70ab7f9,0xb53ab693,0xb517b614,0xb0d7b3ae,
0x34c33365,0x302928b6,0x36d235ce,0x34ff331b,0x385f37cd,0x37bd3665,0x394138d3,0x391b3881,0x3a0939a8,0x3a2939a8,0x3ab33a62,0x3b013a9c,0x3b3d3afc,0x3b9a3b55,0x3ba33b74,0x3bef3bcd,
0x3bb03bd4,0x3bf43c00,0x3b4a3b82,0x3ba33bd5,0x3abd3b08,0x3b0a3b5f,0x3a0d3a69,0x3a2d3aa3,0x393c39a8,0x391639a8,0x385038c9,0x379b3877,0x369937a1,0x34c33637,0x346f3587,0x2ef53288,
0xad972248,0x2d6532a1,0xb487b1f4,0xb13ba91b,0xb77ab608,0xb66bb48d,0xb911b86d,0xb8eab817,0xba31b9a8,0xba50b9a8,0xbb13baaa,0xbb54bae0,0xbbacbb69,0xbbe4bbab,0xbbf8bbdc,0xbbf9bbfe,
0xbbfcbbff,0xbbf5bbc9,0xbbb5bbe3,0xbbe9bc00,0xbb1bbb72,0xbb5cbbb2,0xba35bab1,0xba54bae6,0xb90cb9a8,0xb8e5b9a8,0xb759b862,0xb648b80d,0xb44bb5da,0xb0beb45d,0xac38b160,0x2ec3a57f,
0x29b1abd9,0xb010b414,0x340e30cb,0x30421a48,0x373735ab,0x3625342c,0x39073858,0x38e03802,0x3a3939a8,0x3a5839a8,0x3b243ab8,0x3b633aed,0x3bbd3b7b,0x3bee3bb9,0x3bfe3be9,0x3bef3c00,
0x3bff3bf8,0x3be93baf,0x3bc53bee,0x3bf23c00,0x3b2c3b84,0x3b6a3bc0,0x3a3d3abf,0x3a5c3af3,0x390239a8,0x38db39a8,0x3715384d,0x360237ee,0x33a2357c,0x2f8b33f7,0x25e43036,0xb0bea3db,
0x96482f0e,0x316c34d5,0xb328af40,0xae912852,0xb6f4b54c,0xb5dfb396,0xb8fdb842,0xb8d6b7d8,0xba41b9a8,0xba60b9a8,0xbb35bac6,0xbb71baf9,0xbbccbb8c,0xbbf5bbc6,0xbc00bbf3,0xbbe2bbff,
0xbc00bbed,0xbbdabb91,0xbbd3bbf7,0xbbf8bbfd,0xbb3dbb95,0xbb78bbcb,0xba45bacc,0xba64baff,0xb8f8b9a8,0xb8d1b9a8,0xb6d2b838,0xb5bcb7c2,0xb2adb51d,0xad97b334,0x251bae14,0x32192aac,
0xa94db115,0xb2c6b593,0x32322ce7,0x2c9cac83,0x36af34ed,0x359932d2,0x38f3382d,0x38cc37ac,0x3a4939a8,0x3a6739a8,0x3b453ad3,0x3b7f3b05,0x3bd93b9d,0x3bfb3bd1,0x3bfe3bfa,0x3bd23bfb,
0x3bfc3bdd,0x3bc83b6e,0x3bdf3bfd,0x3bfd3bf8,0x3b4c3ba4,0x3b853bd6,0x3a4d3ad9,0x3a6b3b0b,0x38ee39a8,0x38c739a8,0x368d3822,0x35763796,0x31b634bd,0x2b43326f,0xac062b75,0xb371adb0,
0x340e364e,0x36a43887,0xa94d2edc,0x2d333408,0xb552b20d,0xb432ade2,0xb8c1b780,0xb899b6cc,0xba6fb9a8,0xba8cb9a8,0xbb8bbb11,0xbbb8bb3e,0xbbfebbdb,0xbbf9bbf7,0xbbbdbbf4,0xbb47bbbe,
0xbbb2bb46,0xbb35ba7c,0xbbffbbf0,0xbbf6bbb4,0xbb92bbe0,0xbbbdbbf9,0xba73bb17,0xba90bb43,0xb8bcb9a8,0xb894b9a8,0xb52fb76a,0xb40eb6b5,0xa6adb1aa,0x2e2dad1a,0x34633004,0x36f43451,
0xb4b7b705,0xb742b8d8,0x217fb099,0xaf27b499,0x350b3147,0x33d32c51,0x38b73753,0x388e369e,0x3a7639a8,0x3a9339a8,0x3b983b1d,0x3bc23b49,0x3c003be4,0x3bf33bfb,0x3ba53beb,0x3b213baa,
0x3b983b1a,0x3b0d3a3f,0x3c003be5,0x3bef3b9e,0x3b9e3be8,0x3bc63bfd,0x3a7a3b22,0x3a973b4e,0x38b239a8,0x388939a8,0x34e7373d,0x33893687,0x9cb630e4,0xb0102b11,0xb50bb12e,0xb790b4e1,
0x355e37b7,0x37dd3927,0x251b31c3,0x308d3529,0xb4c3b080,0xb340a97f,0xb8adb726,0xb884b670,0xba7eb9a8,0xba9bb9a8,0xbba3bb28,0xbbcbbb53,0xbc00bbec,0xbbebbbfe,0xbb89bbdf,0xbaf7bb93,
0xbb7abae9,0xbae1b9fe,0xbbffbbd7,0xbbe6bb86,0xbba9bbef,0xbbcfbbff,0xba81bb2e,0xba9ebb58,0xb8a8b9a8,0xb87fb9a8,0xb49fb710,0xb2f7b659,0x2884b01d,0x3109a7da,0x35b13257,0x38153570,
0xb602b832,0xb83ab972,0xaa7ab2ea,0xb185b5b6,0x347b2f72,0x32ad24b6,0x38a336f9,0x387a3642,0x3a8539a8,0x3aa239a8,0x3bae3b33,0x3bd33b5d,0x3bfd3bf2,0x3be13c00,0x3b6a3bd0,0x3acb3b79,
0x3b593ab5,0x3ab339ba,0x3bfc3bc7,0x3bdc3b6b,0x3bb33bf5,0x3bd73c00,0x3a893b39,0x3aa53b62,0x389e39a8,0x387439a8,0x345736e3,0x3263362b,0xac382eaa,0xb2011e48,0xb654b37d,0xb85fb5fd,
0xb99ab997,0xb89fb873,0xb99eb99c,0xb8f5b8ca,0xb9a3b9a0,0xb947b91e,0xb9a7b9a5,0xb995b96e,0xb9abb9a9,0xb9e0b9bb,0xb9b0b9ae,0xba26ba03,0xb9b4b9b2,0xba68ba48,0xb9b9b9b7,0xbaa6ba88,
0xb9d3b9d9,0xba9fbac0,0xb9c6b9cc,0xba59ba7d,0xb9b9b9bf,0xba0eba34,0xb9abb9b2,0xb9bdb9e6,0xb99eb9a5,0xb967b993,0xb991b997,0xb90db93b,0xb983b98a,0xb8aeb8de,0xb975b97c,0xb84cb87e,
0x395e3953,0x385c3824,0x3975396a,0x38c83892,0x398c3981,0x392f38fc,0x39a33997,0x39913961,0x39b939ae,0x39ec39bf,0x39cf39c4,0x3a423a18,0x39e439d9,0x3a913a6a,0x39f939ef,0x3ad93ab6,
0x3a0a3a18,0x3acb3af0,0x39ec39fb,0x3a7b3aa4,0x39cf39de,0x3a223a4f,0x39b039bf,0x39c139f3,0x399139a0,0x395a398e,0x39713981,0x38eb3923,0x39503961,0x387638b1,0x392f3940,0x37f63839,
0xb921b90b,0xb816b7a4,0xb94bb936,0xb89ab859,0xb975b961,0xb917b8d9,0xb99eb98a,0xb98cb953,0xb9c6b9b2,0xb9f9b9c4,0xb9ecb9d9,0xba5dba2c,0xba12b9ff,0xbab7ba8b,0xba36ba24,0xbb07bae1,
0xba3eba53,0xbaf5bb1d,0xba12ba28,0xba9bbaca,0xb9e4b9fb,0xba36ba6a,0xb9b4b9cc,0xb9c6b9ff,0xb983b99c,0xb94bb98a,0xb950b96a,0xb8c8b90b,0xb91cb936,0xb83cb883,0xb8e6b901,0xb750b7e6,
0x38e138c0,0x379e36fc,0x39213901,0x386b381e,0x395e3940,0x38fe38b6,0x399a397c,0x39883944,0x39d339b7,0x3a0539c8,0x3a0a39ef,0x3a773a40,0x3a3e3a24,0x3adc3aab,0x3a703a57,0x3b333b09,
0x3a703a8b,0x3b1c3b47,0x3a363a53,0x3abb3aed,0x39f93a18,0x3a4a3a84,0x39b939d9,0x39ca3a0c,0x39753997,0x393d3985,0x392f3953,0x38a438f2,0x38e6390b,0x38003854,0x389a38c0,0x36a73756,
0xb70db651,0xb4aeb309,0xb83cb7c5,0xb6ebb5d1,0xb8e6b892,0xb880b7fb,0xb983b936,0xb971b8fc,0xba12b9cc,0xba42b9de,0xba91ba53,0xbaefba9d,0xbafebaca,0xbb74bb37,0xbb5abb2e,0xbbcebba6,
0xbb40bb6c,0xbbb2bbd8,0xbad9bb0f,0xbb43bb80,0xba5dba9d,0xbaa6bafa,0xb9cfba18,0xb9e0ba48,0xb92fb981,0xb8f5b96e,0xb880b8d9,0xb7d5b873,0xb788b824,0xb590b6b8,0xb5fab6c3,0xb251b460,
0x367935a2,0x34113197,0x380b374b,0x3684354f,0x38cd386e,0x386637af,0x397e3928,0x396c38ed,0x3a1e39d1,0x3a4e39e2,0x3aa93a66,0x3b043aaf,0x3b1f3ae7,0x3b8c3b4e,0x3b7d3b51,0x3be03bbd,
0x3b613b8d,0x3bc73be8,0x3af53b2e,0x3b5a3b97,0x3a703ab6,0x3ab73b0f,0x39d33a24,0x39e43a53,0x3921397c,0x38e6396a,0x385c38c0,0x37883859,0x370d37e6,0x350e3651,0x3549362e,0x30de3383,
0xb5e2b4f0,0xb2e4b023,0xb7b4b6cf,0xb61db4cc,0xb8b4b849,0xb84cb761,0xb97ab919,0xb967b8de,0xba2ab9d5,0xba59b9e6,0xbac1ba79,0xbb19bac0,0xbb3dbb03,0xbba2bb65,0xbb9cbb70,0xbbefbbd0,
0xbb7fbbaa,0xbbd8bbf4,0xbb10bb4c,0xbb6fbbac,0xba82bacd,0xbac8bb23,0xb9d7ba30,0xb9e8ba5f,0xb912b978,0xb8d7b965,0xb836b8a7,0xb73ab83e,0xb690b783,0xb48ab5e8,0xb496b596,0xaecfb244,
0x3549343b,0x31a42d58,0x37503651,0x35b33447,0x389a3824,0x38313713,0x3975390b,0x396338cf,0x3a3639d9,0x3a6539ea,0x3ad93a8b,0x3b2d3ad0,0x3b5a3b1d,0x3bb53b7a,0x3bb73b8d,0x3bf93be0,
0x3b9a3bc3,0x3be73bfc,0x3b2a3b67,0x3b833bbe,0x3a943ae4,0x3ad93b37,0x39db3a3c,0x39ec3a6a,0x39033973,0x38c83961,0x3811388d,0x36eb3824,0x3611371e,0x3405357e,0x33c034fc,0x2bc03103,
0xb061a8cf,0x25b230ac,0xb549b383,0xb32eae84,0xb816b6c3,0xb750b57e,0xb95eb8c0,0xb94bb883,0xba70b9ef,0xba9bb9ff,0xbb40bae1,0xbb83bb1d,0xbbc7bb8d,0xbbf5bbcc,0xbbffbbed,0xbbeabbff,
0xbbf2bc00,0xbbfebbe3,0xbb96bbcf,0xbbd2bbf9,0xbae9bb49,0xbb25bb8b,0xb9f1ba75,0xba01baa1,0xb8b9b95c,0xb87bb949,0xb69bb809,0xb555b734,0xb2fdb514,0xad71b2bf,0xa376af7e,0x31662966,
0x2e39a052,0xabf2b21f,0x34de3276,0x32512c5e,0x37f63673,0x3718352c,0x395a38b1,0x39473873,0x3a7b39f3,0x3aa63a03,0x3b523af0,0x3b923b2c,0x3bd63b9f,0x3bfb3bd8,0x3c003bf6,0x3bda3bfc,
0x3bfa3bff,0x3bf93bd1,0x3ba73bdd,0x3bdd3bfd,0x3af83b5b,0x3b333b99,0x39f53a80,0x3a053aab,0x38a93957,0x386b3944,0x364b37db,0x350236fc,0x31ee34a8,0x2a9331e2,0xa8062cf4,0xb2d8ad3f,
0xab5c2af8,0x2e843390,0xb472b166,0xb172a86b,0xb7bfb622,0xb6e0b4d8,0xb955b8a2,0xb942b863,0xba86b9f7,0xbab0ba08,0xbb64bb00,0xbba0bb39,0xbbe3bbaf,0xbbffbbe2,0xbbfdbbfd,0xbbc6bbf5,
0xbbffbbfa,0xbbf1bbba,0xbbb7bbe8,0xbbe7bc00,0xbb07bb6c,0xbb40bba6,0xb9f9ba8b,0xba0abab6,0xb89ab953,0xb85cb940,0xb5fab7a4,0xb4aeb6c3,0xb0deb43b,0xa484b103,0x2cf4a8cf,0x34232fc9,
0x2484ae6b,0xb086b47e,0x34053055,0x30931248,0x378835d1,0x36a73484,0x39503892,0x393d3854,0x3a9139fb,0x3abb3a0c,0x3b743b0f,0x3bad3b47,0x3bed3bbe,0x3c003beb,0x3bf63c00,0x3bae3beb,
0x3c003bf0,0x3be53ba0,0x3bc53bf2,0x3bef3c00,0x3b163b7c,0x3b4d3bb3,0x39fd3a96,0x3a0e3ac0,0x388b394e,0x384c393b,0x35a8376c,0x345a368a,0x2f97339c,0xa4203023,0xafe298b6,0xb4d8b128,
0x31c93531,0x355b37e0,0xaf652839,0x9d7f315a,0xb66db42f,0xb584b1b0,0xb939b844,0xb925b803,0xbac5ba10,0xbaecba20,0xbbb9bb53,0xbbdfbb82,0xbbffbbf2,0xbbe3bc00,0xbb91bbde,0xbaf7bb8a,
0xbbd6bb81,0xbb7cbadf,0xbbf5bbfd,0xbc00bbdd,0xbb5abbbe,0xbb88bbe3,0xba12baca,0xba22baf0,0xb83cb936,0xb7f6b923,0xb405b651,0xb15ab567,0x2a61ae84,0x31e22052,0x358a3269,0x381935a8,
0xb309b5e2,0xb5f4b841,0x2da3ac44,0xa5b2b269,0x363433b4,0x35493103,0x39343834,0x392137e6,0x3acf3a14,0x3af53a24,0x3bc43b60,0x3be73b8d,0x3bfb3bf8,0x3bd63bff,0x3b703bce,0x3ac63b6d,
0x3bc53b5f,0x3b5d3aad,0x3bfa3bf9,0x3bff3bcf,0x3b663bc9,0x3b923bea,0x3a163ad4,0x3a263afa,0x382c3931,0x37d5391e,0x335f3617,0x30ac352c,0xad582cc2,0xb2f0a89d,0xb63ab3a8,0xb869b63f,
0x34233690,0x368a3890,0xabc02e6b,0x2a613377,0xb5fab309,0xb50eb055,0xb92fb824,0xb91cb7c5,0xbad9ba18,0xbafeba28,0xbbcebb6c,0xbbedbb97,0xbbf6bbfc,0xbbc7bbfd,0xbb4cbbba,0xba93bb4d,
0xbbafbb38,0xbb3cba77,0xbbfebbf2,0xbbfcbbbf,0xbb72bbd3,0xbb9cbbf0,0xba1abadd,0xba2abb03,0xb81cb92d,0xb7b4b919,0xb2b3b5dc,0xaffbb4f0,0x2f7ea9fd,0x33fd2c12,0x36e53472,0x38b636d4,
0xb4c0b73a,0xb71eb8dc,0x2839b048,0xacf4b441,0x35bf325d,0x34d22f4c,0x392a3813,0x391737a4,0x3ae23a1c,0x3b073a2c,0x3bd73b77,0x3bf33ba1,0x3bee3bff,0x3bb63bfa,0x3b233ba4,0x3a5b3b2a,
0x3b973b0d,0x3b183a3e,0x3c003be9,0x3bf73bad,0x3b7d3bdb,0x3ba63bf5,0x3a1e3ae7,0x3a2e3b0c,0x380b3928,0x37933914,0x320735a2,0x2e9d34b4,0xb0d124e9,0xb484add5,0xb78eb50e,0xb901b767,
0xb97239ba,0x39dc3996,0xb8323ab5,0x3ad0385d,0x3927b9fe,0xba1fb94d,0x37b7bae9,0xbb02b807,0xb8d83a3f,0x3a5e3900,0xb7053b1a,0x3b30375e,0x3887ba7c,0xba99b8b0,0x364ebb46,0xbb5ab6aa,
0xb90039dc,0x3a3f3972,0xad7e3be6,0x3bf83115,0x3807ba99,0xbae9b887,0xabd9bc00,0xbbfca248,0xb5f13b30,0x3b6e3705,0x32a13bed,0x3bd4b04e,0x3365bba0,0xbbc9b4d5,0xb593bbaf,0xbb803475,
0xb88739fe,0x3a99394d,0x35f13bbc,0x3b6eb414,0x3593bb1a,0xbb80b75e,0xb8b0bb02,0xba7c37b7,0xaf0e3bc9,0x3bf43365,0x3a1f39dc,0x3927b972,0xb04ebc00,0xbbed2248,0xbb30b85d,0xb7053ab5,
0xb8073a1f,0x3ae93927,0x39fe3a3f,0x394db900,0x31dbbb80,0xbbddb593,0xbb6eb832,0xb5f13ad0,0x31153c00,0x3be62248,0x3bff32a1,0x28b6bbd4,0xb7b7bb91,0xbb023534,0xbba0304e,0x34d53bed,
0xb7053a3f,0x3b303900,0x3bbc375e,0x3414bb1a,0x2248bbc9,0xbc00b365,0xbbdda8b6,0x31db3bff,0x36aa3bd4,0x3b46b2a1,0x3a7cb64e,0xb8b0bb5a,0xba1fba5e,0xb92738d8,0xb7b739fe,0x3b02394d,
0xb5f13a5e,0x3b6e38d8,0x3bd42bd9,0xb2a1bbfc,0xb115bbf4,0xbbe6af0e,0xb9dc375e,0x39723b1a,0x39273b46,0x3a1fb6aa,0x3475bad0,0xbbafb832,0xbb91b887,0xb5343a99,0x34143c00,0x3bbc2248,
0xb4d53a7c,0x3ba038b0,0x3a3fb593,0xb900bb80,0xb534bc00,0xbb912248,0xb4143ab5,0x3bbc385d,0x3a993a5e,0x3887b8d8,0xb5f1bbfc,0xbb6e2bd9,0xbbffb475,0x28b63baf,0x3ad03a1f,0x3832b927,
0xb3653a99,0x3bc93887,0x36aab996,0xbb46b9ba,0xb7b7bbed,0xbb02304e,0x34d53bfc,0x3ba02bd9,0x3b913927,0x3534ba1f,0xbae9ba3f,0xb8073900,0xbb5a28b6,0x364e3bff,0x3bd43115,0xb2a1bbe6,
0xb1153ab5,0x3be6385d,0xa8b6bb6e,0xbbffb5f1,0xb900bbbc,0xba3f3414,0x3a1f3b30,0x3927b705,0x3bfc375e,0x2bd9bb1a,0xbbedb475,0x304e3baf,0xb9ba3593,0x39963b80,0x3887b832,0xba99bad0,
0xad7e3ad0,0x3bf83832,0xb7b7bbff,0xbb0228b6,0xb9febb6e,0xb94d35f1,0x3bed3887,0x304eba99,0x3bd43414,0xb2a1bbbc,0xb9963534,0x39ba3b91,0xb6aa3900,0x3b463a3f,0xb115bba0,0xbbe6b4d5,
0xa2483ae9,0x3c003807,0xba99bb30,0xb8873705,0xbad0bb02,0xb83237b7,0x3b462d7e,0xb6aabbf8,0x3b1a28b6,0xb75ebbff,0xaf0e3a7c,0x3bf438b0,0xabd93ab5,0x3bfc385d,0xba5ebb5a,0xb8d8364e,
0x2bd93b02,0x3bfc37b7,0xbbedb927,0xb04e3a1f,0xbb6eba7c,0xb5f138b0,0x385db6aa,0xbab5bb46,0x39dcb1db,0xb972bbdd,0x38323c00,0x3ad02248,0x34d53bbc,0x3ba03414,0xbbf4b705,0x2f0e3b30,
0x304e3b1a,0x3bed375e,0xbb91b475,0x35343baf,0xbbd4b9dc,0xb2a13972,0x2248ba7c,0xbc00b8b0,0x3832b64e,0xbad0bb5a,0x3b803a99,0x3593b887,0x39003bfc,0x3a3fabd9,0xb9273414,0x3a1f3bbc,
0x32a13b30,0x3bd43705,0xb996304e,0x39ba3bed,0xbbffb927,0xa8b63a1f,0xb832bbf4,0xbad0af0e,0x3475b8b0,0xbbafba7c,0x3ba03593,0xb4d5bb80,0x3ae93b6e,0x3807b5f1,0x2bd93a99,0x3bfc3887,
0x34753b46,0x3baf36aa,0xb4d53832,0x3ba03ad0,0xbbedb85d,0x304e3ab5,0xbb30bb5a,0xb705364e,0x2248b9fe,0xbc00b94d,0x3887b414,0xba99bbbc,0x3be63a1f,0x3115b927,0x39dc3bf4,0x3972af0e,
0x35933b5a,0x3b80364e,0x31153a99,0x3be63887,0xbba0b705,0x34d53b30,0xbbf4b8d8,0x2f0e3a5e,0xb414bb02,0xbbbcb7b7,0xabd9ba1f,0xbbfcb927,0x3bd43832,0xb2a1bad0,0x3c003972,0xa248b9dc,
0x36aa3b6e,0x3b4635f1,0x38b03bdd,0x3a7c31db,0xbb1ab534,0x375e3b91,0xba3fb04e,0x39003bed,0xb807bbaf,0xbae9b475,0xb94dbbf8,0xb9fead7e,0x3ab53365,0xb85dbbc9,0x39ba28b6,0xb996bbff,
0x37b73b80,0x3b023593,0x3b1a3bc9,0x375eb365,0xba5eb2a1,0x38d83bd4,0xb53435f1,0x3b913b6e,0xb9babbfc,0xb996abd9,0xbbddbae9,0xb1db3807,0x38b0ad7e,0xba7cbbf8,0x28b6b900,0xbbffba3f,
0x385d3b91,0x3ab53534,0x3c003a5e,0x2248b8d8,0xb972ad7e,0x39dc3bf8,0x33653a3f,0x3bc93900,0xbb02bbe6,0xb7b73115,0xbb1ab6aa,0x375e3b46,0x3414b64e,0xbbbcbb5a,0xb94dbbdd,0xb9feb1db,
0x38d83ba0,0x3a5e34d5,0x3b3037b7,0xb705bb02,0xb85d28b6,0x3ab53bff,0x39ba3be6,0x39963115,0xbbc9bb6e,0xb36535f1,0xb6aa31db,0x3b463bdd,0xaf0eb94d,0xbbf4b9fe,0xbbf8bae9,0xad7e3807,
0x394d3baf,0x39fe3475,0x38d82d7e,0xba5ebbf8,0xb64e3115,0x3b5a3be6,0x3bd43b80,0x32a1b593,0xbbffba99,0x28b63887,0x336539ba,0x3bc93996,0xb75ebae9,0xbb1ab807,0xba3fb534,0x39003b91,
0x39ba3bbc,0x39963414,0x31dbb534,0xbbddbb91,0xb3653475,0x3bc93baf,0x3b803927,0xb593ba1f,0xbba0b972,0x34d539dc,0x3a3f3be6,0x39003115,0xb9febbd4,0xb94db2a1,0xb04e35f1,0x3bed3b6e,
0x3a1f3bc9,0x39273365,0xb475b972,0xbbafb9dc,0xabd9364e,0x3bfc3b5a,0x38d831db,0xba5ebbdd,0xbab5b807,0x385d3ae9,0x3c003b30,0x2248b705,0xbb80bbf4,0xb5932f0e,0x38b03b1a,0x3a7c375e,
0x3a7c3bd4,0x38b032a1,0xb972bb5a,0xb9dcb64e,0x2f0e3807,0x3bf43ae9,0x2d7eb534,0xbbf8bb91,0xb94db4d5,0x39fe3ba0,0x3a5e37b7,0xb8d8bb02,0xbc00bb46,0x224836aa,0x3bdd3bc9,0x31dbb365,
0x3ad03bdd,0x383231db,0xbb80bc00,0xb5932248,0x347538d8,0x3baf3a5e,0xb75eb9fe,0xbb1ab94d,0xb705ad7e,0x3b303bf8,0x3414af0e,0xbbbcbbf4,0xbb6eb9dc,0x35f13972,0x3ab538b0,0xb85dba7c,
0x3b1a3be6,0x375e3115,0xbbf4bb46,0x2f0e36aa,0x37053996,0x3b3039ba,0xbae9bbd4,0xb807b2a1,0xb1db304e,0x3bdd3bed,0xb64eb94d,0xbb5ab9fe,0xb9dcb7b7,0x39723b02,0x3365ad7e,0xbbc9bbf8,
0x3b5a3bed,0x364e304e,0xbab5b94d,0x385d39fe,0x38b03a3f,0x3a7c3900,0xbbffbba0,0x28b634d5,0x2d7e3593,0x3bf83b80,0xbb02bbc9,0xb7b7b365,0xb705b1db,0x3b303bdd,0xb807b9ba,0xbae9b996,
0x3b913bf4,0x35342f0e,0xb807b4d5,0x3ae93ba0,0x39ba3ad0,0x39963832,0xba99b972,0x388739dc,0x3593385d,0x3b803ab5,0xbbe6bb6e,0x311535f1,0xad7e304e,0x3bf83bed,0xbbafbbfc,0xb475abd9,
0x3bbc3bf8,0x34142d7e,0xabd92f0e,0x3bfc3bf4,0x3a993b46,0x388736aa,0xb64eb365,0x3b5a3bc9,0x38b039ba,0x3a7c3996,0xb972b85d,0x39dc3ab5,0x34753705,0x3baf3b30,0xbb1aba5e,0x375e38d8,
0x3bdd3bfc,0x31db2bd9,0x364e3807,0x3b5a3ae9,0x3b463ba0,0x36aa34d5,0x31153475,0x3be63baf,0x3a3f3ad0,0x39003832,0xad7e28b6,0x3bf83bff,0x38d83996,0x3a5e39ba,0xb534b2a1,0x3b913bd4,
0x3bf43bff,0x2f0e28b6,0x3a1f3a7c,0x392738b0,0x3bbc3bdd,0x341431db,0x394d39ba,0x39fe3996,0x3b5a3b91,0x364e3534,0x385d38d8,0x3ab53a5e,0x3ad03b1a,0x3832375e,0x36aa37b7,0x3b463b02,
0x3bff3c00,0x28b62248,0x3bc93bd4,0x336532a1,0x3bf83bfc,0x2d7e2bd9,0x3baf3bbc,0x34753414,0x3bed3bf4,0x304e2f0e,0x3b913ba0,0x353434d5,0x3bdd3be6,0x31db3115,0x3b6e3b80,0x35f13593,
0xb5933b6e,0x3b8035f1,0xb1153bdd,0x3be631db,0x34d5bb91,0xbba0b534,0x2f0ebbed,0xbbf4b04e,0xb4143baf,0x3bbc3475,0xabd93bf8,0x3bfc2d7e,0x32a1bbc9,0xbbd4b365,0x2248bbff,0xbc00a8b6,
0x37b73b46,0x3b02b6aa,0x3b1a3832,0x375ebad0,0xb8d8bab5,0xba5e385d,0xbb91b64e,0xb5343b5a,0x39ba39fe,0x3996b94d,0x3bdd3414,0x31dbbbbc,0xba7cb927,0xb8b03a1f,0xbbffaf0e,0xa8b63bf4,
0x3bd43534,0x32a1bb91,0x39bab8d8,0xb996ba5e,0xbbffad7e,0x28b63bf8,0xb8323a3f,0x3ad03900,0x3bafb115,0xb475bbe6,0x34d5bb46,0xbba0b6aa,0xbae9364e,0x38073b5a,0xabd93bdd,0x3bfc31db,
0x3a5eb75e,0xb8d8bb1a,0xb705bbaf,0xbb303475,0xb85d39dc,0x3ab53972,0x39ba3a7c,0x3996b8b0,0x3365bb5a,0xbbc9b64e,0xbb46b887,0xb6aa3a99,0x2f0e3bfc,0x3bf42bd9,0x3bf83414,0x2d7ebbbc,
0x2bd9bbaf,0xbbfcb475,0xbbedad7e,0x304e3bf8,0x35f13be6,0x3b6eb115,0x3ab5b593,0xb85dbb80,0xb9dcba99,0xb9723887,0xb83239ba,0x3ad03996,0x3ba03807,0x34d5bae9,0x2f0ebb91,0xbbf4b534,
0xb9babae9,0xb9963807,0xb1db3b30,0x3bdd3705,0x3bc937b7,0x3365bb02,0xb593bbf8,0xbb802d7e,0xbba028b6,0x34d53bff,0x3a3f3a7c,0x3900b8b0,0x394db85d,0xb9febab5,0xbbedb64e,0xb04e3b5a,
0xbbf8b365,0x2d7e3bc9,0x3b0239dc,0x37b7b972,0x39feb64e,0xb94dbb5a,0xbbedb1db,0x304e3bdd,0xb2a13ae9,0x3bd43807,0x39bab705,0xb996bb30,0xb6aabbf4,0xbb462f0e,0xb1153b1a,0x3be6375e,
0xb8b0385d,0x3a7c3ab5,0x39dcb5f1,0xb972bb6e,0xaf0ebbbc,0xbbf4b414,0xad7e3b30,0x3bf83705,0x39fe3b1a,0x394db75e,0xb8d8bbaf,0xba5e3475,0xbc00b593,0x22483b80,0x3bdd3832,0x31dbbad0,
0x33653bdd,0x3bc931db,0xb6aabc00,0xbb462248,0xbb02ba5e,0xb7b738d8,0x3ba0394d,0x34d5b9fe,0x3b912d7e,0xb534bbf8,0xbae92f0e,0x38073bf4,0xb64e3972,0x3b5a39dc,0x32a1ba7c,0xbbd4b8b0,
0x3b1a3a7c,0x375eb8b0,0xbbf4b593,0x2f0e3b80,0xbb30a248,0x37053c00,0x3807b85d,0xbae9bab5,0x31dbba5e,0xbbddb8d8,0x364e3bfc,0x3b5a2bd9,0x39723baf,0x39dcb475,0xbbc9b927,0xb3653a1f,
0x3b6e304e,0xb5f1bbed,0xb2a139fe,0x3bd4394d,0xb1153a3f,0x3be63900,0xb9dcbba0,0xb97234d5,0xba1fbb80,0xb9273593,0x3baf3365,0xb475bbc9,0x3b9131db,0xb534bbdd,0xb41439ba,0x3bbc3996,
0x3534b900,0xbb91ba3f,0x3ae93b1a,0x3807b75e,0x39ba3bc9,0x3996b365,0xba9928b6,0x38873bff,0xbb80b2a1,0x35933bd4,0xb115bb5a,0xbbe6b64e,0x2d7eba5e,0xbbf8b8d8,0x3baf39fe,0x3475b94d,
0xb807bbf8,0xbae9ad7e,0x39feaf0e,0xb94dbbf4,0x3bdd36aa,0xb1dbbb46,0x35f13bc9,0x3b6e3365,0xb11539ba,0x3be63996,0xbbffb85d,0x28b63ab5,0xbb02bb30,0xb7b73705,0x34d5b8d8,0xbba0ba5e,
0xbbddb9fe,0xb1db394d,0xb64ebbbc,0xbb5ab414,0x36aab75e,0xbb46bb1a,0x3be637b7,0xb115bb02,0x3a3f3bc9,0x3900b365,0xad7e39dc,0x3bf83972,0xba5ea248,0x38d83c00,0xbb91bab5,0xb534385d,
0xba3fa8b6,0x39003bff,0xbbf8b8b0,0x2d7e3a7c,0xb807bbdd,0xbae9b1db,0x2bd9b9ba,0xbbfcb996,0x3b6e3534,0xb5f1bb91,0x3bd43a5e,0x32a1b8d8,0x33653b1a,0x3bc9375e,0xb59337b7,0x3b803b02,
0xa8b63996,0x3bff39ba,0xb365385d,0x3bc93ab5,0xbbf8b9fe,0xad7e394d,0xbbafbae9,0xb4753807,0x304eb900,0xbbedba3f,0x3534b75e,0xbb91bb1a,0x3bdd3a7c,0x31dbb8b0,0x3b6e3b46,0x35f1b6aa,
0x39dc3c00,0x3972a248,0x3ad03bd4,0x3832b2a1,0xb9272bd9,0x3a1f3bfc,0xb7b73414,0x3b023bbc,0xba5ebbf4,0xb8d82f0e,0xbb30bba0,0xb70534d5,0x3887b115,0xba99bbe6,0x364eb593,0xbb5abb80,
0x3bf43972,0xaf0eb9dc,0x3a1f3115,0xb927bbe6,0x34143a99,0x3bbc3887,0x39fe3c00,0x394d2248,0xbb5ab705,0x364e3b30,0xb85d304e,0x3ab53bed,0xb832bba0,0xbad0b4d5,0xbb46bbaf,0xb6aa3475,
0x3887abd9,0xba99bbfc,0xb5f1bae9,0xbb6eb807,0x3b803ba0,0x3593b4d5,0x3a7c3475,0xb8b0bbaf,0xaf0e3832,0x3bf43ad0,0x3a1f3bff,0x392728b6,0xbbedb996,0x304e39ba,0xb70532a1,0x3b303bd4,
0xb414ba1f,0xbbbcb927,0xbbfcba3f,0x2bd93900,0x3a993593,0xb887bb80,0xb64ebad0,0xbb5ab832,0x3a7c3c00,0x38b02248,0x39dc32a1,0xb972bbd4,0xb4753534,0x3baf3b91,0x3b1a3bed,0x375eb04e,
0xbb30bbf4,0xb7052f0e,0xb41434d5,0x3bbc3ba0,0x2248b832,0xbc00bad0,0xbbddb9dc,0x31db3972,0x3b46385d,0xb6aabab5,0xb8b0bb6e,0xba7cb5f1,0x3a1f3bed,0x3927304e,0x37b7abd9,0xbb02bbfc,
0xbb5ab8d8,0x364e3a5e,0x3ab53bfc,0x385d2bd9,0xba7cbbf4,0xb8b0af0e,0xa8b6375e,0x3bff3b1a,0x2d7eb6aa,0xbbf8bb46,0xbb02b832,0x37b73ad0,0x3b303887,0xb705ba99,0xbae9bc00,0xb807a248,
0xb4d53115,0x3ba03be6,0x3a3f36aa,0xb900bb46,0xbb91b996,0x353439ba,0x3bbc3bd4,0x3414b2a1,0xba99bbed,0xb887b04e,0x35f139fe,0x3b6e394d,0xa8b6b7b7,0xbbffbb02,0xb832ad7e,0x3ad03bf8,
0x38323a99,0x3ad03887,0xb593b996,0xbb80b9ba,0xb475304e,0x3baf3bed,0x375e2bd9,0xbb1abbfc,0xbb30b927,0x37053a1f,0x3bbc3a3f,0xb414b900,0xbb6ebbff,0xb5f128b6,0x3ab53be6,0x385d3115,
0x3be63bd4,0x3115b2a1,0xbbffbb5a,0x28b6364e,0x39003ae9,0x3a3f3807,0xba1fbb91,0xb927b534,0xabd934d5,0x3bfc3ba0,0xb04eb7b7,0xbbedbb02,0xb9bab6aa,0x39963b46,0x38873365,0xba99bbc9,
0x3a1f3832,0xb927bad0,0xb47528b6,0x3baf3bff,0x3bfc3b6e,0xabd9b5f1,0xba5eb887,0x38d83a99,0x3ab53bbc,0x385d3414,0xbc00bb91,0x22483534,0x35933900,0x3b803a3f,0xba7cbba0,0xb8b0b4d5,
0x2248b414,0xbc00bbbc,0x3a993b91,0x38873534,0x38323475,0xbad0bbaf,0x36aa3927,0x3b463a1f,0x3b1a39dc,0xb75eb972,0xaf0e3115,0x3bf43be6,0x3bfc3bd4,0x2bd9b2a1,0xb8d8b5f1,0x3a5e3b6e,
0xb9febb02,0xb94db7b7,0x3a5e3927,0xb8d8ba1f,0xb64eb8b0,0xbb5aba7c,0x3bd43b46,0xb2a1b6aa,0x28b6b1db,0xbbffbbdd,0x3bc93c00,0x33652248,0x375e3414,0xbb1abbbc,0x3a3f3b30,0x39003705,
0xbbedbba0,0x304e34d5,0xb534b7b7,0xbb91bb02,0xbbd4bbff,0xb2a1a8b6,0x2248b115,0xbc00bbe6,0xbad0bb6e,0xb832b5f1,0x359331db,0xbb80bbdd,0xb900b9fe,0xba3fb94d,0x39273807,0xba1fbae9,
0xb85db705,0x3ab53b30,0xbc00bbed,0x2248304e,0xb9dcb927,0x39723a1f,0xbbc9bbf4,0xb365af0e,0xbb02ba7c,0x37b738b0,0xbb1abb80,0xb75eb593,0xbbbcbb6e,0x341435f1,0xb9feba99,0xb94db887,
0x34753593,0x3baf3b80,0xb4d5b365,0x3ba03bc9,0x304e32a1,0x3bed3bd4,0xb705b5f1,0x3b303b6e,0xa2482bd9,0x3c003bfc,0xb887b807,0x3a993ae9,0xb115ad7e,0x3be63bf8,0xb972b900,0x39dc3a3f,
0x3b463b5a,0x36aa364e,0x3a7c3a99,0x38b03887,0x3b1a3b30,0x375e3705,0x3a3f3a5e,0x390038d8,0x3ae93b02,0x380737b7,0x39fe3a1f,0x394d3927,0x3ab53ad0,0x385d3832,0x39ba39dc,0x39963972,
0x28b63c00,0x3bffa248,0x33653bd4,0x3bc9b2a1,0xad7ebbfc,0xbbf82bd9,0xb475bbbc,0xbbaf3414,0x304e3bf4,0x3bedaf0e,0x35343ba0,0x3b91b4d5,0xb1dbbbe6,0xbbdd3115,0xb5f1bb80,0xbb6e3593,
0x3bf4a8b6,0xaf0ebbff,0x3a1fb8b0,0xb927ba7c,0xbbbc31db,0x34143bdd,0xb94d3996,0x39fe39ba,0x3b5ab534,0xb64ebb91,0x385dba5e,0xbab5b8d8,0xbad0375e,0x38323b1a,0xb6aa3b02,0x3b4637b7,
0xb1dbbbfc,0xbbdd2bd9,0xbb5ab807,0xb64e3ae9,0x36aa3ba0,0x3b46b4d5,0x3be63475,0x3115bbaf,0xb900bad0,0xba3f3832,0xbbf8a8b6,0x2d7e3bff,0x3a5e3996,0x38d8b9ba,0x3b91b2a1,0xb534bbd4,
0xbbbc2d7e,0x34143bf8,0x2bd93bf4,0x3bfc2f0e,0x3a99b6aa,0xb887bb46,0xb64ebbc9,0xbb5a3365,0xb8b03996,0x3a7c39ba,0x39723ab5,0x39dcb85d,0x3475bb30,0xbbafb705,0xbb1ab8d8,0xb75e3a5e,
0x35343bf4,0x3b91af0e,0x3ae9b4d5,0xb807bba0,0xb996bad0,0xb9ba3832,0xb8873972,0x3a9939dc,0x3b80385d,0x3593bab5,0x3115bb6e,0xbbe6b5f1,0xbbf8b04e,0x2d7e3bed,0x34753bfc,0x3bafabd9,
0x3b5ab04e,0xb64ebbed,0xbab5b9fe,0xb85d394d,0xb8b03900,0x3a7c3a3f,0x3bff34d5,0x28b6bba0,0x2d7ebb80,0xbbf8b593,0xbb023365,0x37b73bc9,0x37053bdd,0x3b30b1db,0x3807b996,0xbae9b9ba,
0xb75ebbe6,0xbb1a3115,0xaf0e3b46,0x3bf436aa,0x3b303996,0x3705b9ba,0xb807bbd4,0xbae932a1,0xbbddb04e,0x31db3bed,0x3b5a394d,0x364eb9fe,0x3972b7b7,0xb9dcbb02,0xbbc9ad7e,0x33653bf8,
0xbad031db,0x38323bdd,0x3b802248,0xb593bc00,0x3475ba5e,0xbbafb8d8,0xb75e394d,0x3b1a39fe,0x37053bf8,0x3b30ad7e,0xb414bbf4,0xbbbcaf0e,0xbb6eb972,0xb5f139dc,0x3ab53a7c,0x385db8b0,
0x38b03bd4,0x3a7cb2a1,0xb9dcbb5a,0xb972364e,0xbbf4b807,0xaf0e3ae9,0x3bf83534,0xad7ebb91,0x39feb4d5,0xb94dbba0,0xb8d837b7,0x3a5e3b02,0xa2483b46,0x3c0036aa,0xb1dbbbc9,0xbbddb365,
0x3a1fb365,0xb927bbc9,0xb47539dc,0x3baf3972,0x2bd93b5a,0x3bfc364e,0xb8d8bbdd,0xba5e31db,0xbab5bae9,0xb85d3807,0x3c003705,0xa248bb30,0x3b802f0e,0xb593bbf4,0xb8b0375e,0x3a7c3b1a,
0xb996bbbc,0xb9ba3414,0x3bdd3534,0xb1dbbb91,0x3bc93475,0xb365bbaf,0xb5933927,0x3b803a1f,0xb4d53972,0x3ba039dc,0xb900bbe6,0xba3f3115,0xb94dbbd4,0xb9fe32a1,0x3bed35f1,0xb04ebb6e,
0xb94d3475,0x39fe3baf,0xb8d8bbf8,0xba5e2d7e,0xb64ebbe6,0xbb5ab115,0x3bd43593,0xb2a1bb80,0x3bff3887,0x28b6ba99,0xb3653996,0x3bc939ba,0xb75e3807,0x3b1a3ae9,0xba3fbb91,0xb9003534,
0x3a5e3ba0,0x38d8b4d5,0xb70537b7,0x3b303b02,0xbab5a8b6,0x385d3bff,0xb996bbe6,0xb9ba3115,0xb365bb6e,0xbbc9b5f1,0x3b4631db,0xb6aabbdd,0x3bf4394d,0x2f0eb9fe,0x2d7e3ae9,0x3bf83807,
0x385db534,0xbab5bb91,0x3c0038d8,0xa248ba5e,0x39723bf8,0x39dcad7e,0xb3653900,0x3bc93a3f,0xbb02b115,0x37b73be6,0xbb1abb46,0xb75e36aa,0xb414bb5a,0xbbbcb64e,0x394db1db,0xb9febbdd,
0xbb02bb80,0xb7b73593,0xb75ebbc9,0xbb1ab365,0x38d8b2a1,0xba5ebbd4,0x3b9135f1,0xb534bb6e,0x39963bfc,0x39baabd9,0x31db3ae9,0x3bdd3807,0xba7cad7e,0x38b03bf8,0xbbffb900,0x28b63a3f,
0xb6aa35f1,0x3b463b6e,0xb8b031db,0x3a7c3bdd,0xbb1abb91,0xb75e3534,0xba3fbbed,0xb900304e,0x3807b475,0xbae9bbaf,0x394dad7e,0xb9febbf8,0x3ab53bc9,0x385db365,0x39ba3bff,0x3996a8b6,
0x3b803b5a,0x3593b64e,0x3be63a99,0x3115b887,0xb4d53705,0x3ba03b30,0xaf0e38d8,0x3bf43a5e,0xbbbcbb02,0xb41437b7,0xbbfcba1f,0xabd93927,0x32a1b832,0xbbd4bad0,0x2248b972,0xbc00b9dc,
0x3475b6aa,0xbbafbb46,0xb4d5bad0,0xbba0b832,0x3bed3ab5,0x304eb85d,0x3b30364e,0xb705bb5a,0x2248394d,0x3c0039fe,0x38873bbc,0x3a993414,0xbbe6b927,0x31153a1f,0xb9dcaf0e,0x39723bf4,
0xbbd4bb30,0xb2a13705,0xb9bab04e,0x39963bed,0xa8b6b927,0xbbffba1f,0xbad0bbf4,0xb8322f0e,0x3baf38b0,0xb475ba7c,0x34d5b593,0xbba0bb80,0x38073b6e,0x3ae935f1,0x3bfc3a99,0x2bd9b887,
0xb04e375e,0x3bed3b1a,0x3b913baf,0x3534b475,0xbbd4b972,0x32a139dc,0x224838b0,0x3c003a7c,0xb832bb5a,0xbad0b64e,0xbb80b887,0x35933a99,0x39002bd9,0xba3fbbfc,0xb927bbbc,0xba1fb414,
0x3bfc3b02,0x2bd9b7b7,0xb04eb927,0xbbedba1f,0x35f13a7c,0x3b6e38b0,0x3ab536aa,0xb85dbb46,0xb972b1db,0x39dc3bdd,0x3ad03c00,0x3832a248,0xbba0bbbc,0xb4d53414,0xaf0e3705,0x3bf43b30,
0xa248b807,0xbc00bae9,0xba99b705,0x38873b30,0x3ad037b7,0xb832bb02,0xbb46bbf8,0xb6aa2d7e,0x3b1a3bff,0x375ea8b6,0xaf0eb8b0,0xbbf4ba7c,0x2bd9385d,0x3bfc3ab5,0x3a5e364e,0xb8d8bb5a,
0xbbf8bad0,0x2d7e3832,0x3b023bff,0x37b728b6,0xb94dbb6e,0xb9feb5f1,0x304e3887,0x3bed3a99,0x32a1b414,0xbbd4bbbc,0xb9bab534,0x39963b91,0x3b463900,0xb6aaba3f,0xbbe6bba0,0xb11534d5,
0x3115385d,0x3be63ab5,0x28b6b5f1,0xbbffbb6e,0xb900b414,0x3a3f3bbc,0x3a1f3705,0xb927bb30,0xbbfcbb1a,0x2bd9375e,0x3bed3baf,0x304eb475,0xb9babb80,0xb996b593,0x38873ad0,0x3a993832,
0x3bc93a99,0xb365b887,0xbb46b996,0x36aa39ba,0x3b023bed,0x37b7304e,0xbba0bbfc,0xb4d52bd9,0x35343927,0x3b913a1f,0xb807ba3f,0xbae9b900,0xb64ea8b6,0x3b5a3bff,0x32a1b115,0xbbd4bbe6,
0xb4d5b8b0,0xbba0ba7c,0x3a3f3b80,0x39003593,0x35342248,0xbb91bc00,0x3414385d,0x3bbc3ab5,0x3a9938d8,0xb887ba5e,0xb5f1abd9,0x3b6e3bfc,0x3bff3baf,0x28b6b475,0xbad0b927,0x38323a1f,
0xbb6eba5e,0x35f138d8,0x32a1abd9,0xbbd4bbfc,0xbbe6bbf4,0xb1152f0e,0x3972375e,0xb9dcbb1a,0xba1fbb46,0xb927b6aa,0x3baf3ad0,0xb475b832,0xb534b887,0xbb91ba99,0x3bbc3c00,0x3414a248,
0x37053900,0x3b303a3f,0xbbbcbb1a,0x3414375e,0x22483365,0x3c003bc9,0xbbddbbff,0xb1db28b6,0xb6aab2a1,0x3b463bd4,0xba7cbb5a,0xb8b0b64e,0xba1fb8d8,0x39273a5e,0xb7b7b94d,0xbb02b9fe,
0x3ae93a1f,0xb807b927,0x394d3a3f,0x39fe3900,0x3bdd3b80,0xb1dbb593,0x35f13832,0x3b6e3ad0,0x3be63c00,0x3115a248,0x28b632a1,0x3bff3bd4,0x3b023b91,0x37b73534,0xb4d5b04e,0x3ba03bed,
0xb887b94d,0xba99b9fe,0x35f13414,0xbb6ebbbc,0xb593b75e,0xbb80bb1a,0x38b037b7,0xba7cbb02,0xaf0eb365,0xbbf4bbc9,0x3a1f3972,0xb927b9dc,0x304e2248,0xbbedbc00,0x3b303ab5,0xb705b85d,
0xba3fb9dc,0x39003972,0xbbf8bbe6,0x2d7e3115,0xbae9ba99,0x38073887,0xbbfcbc00,0xabd92248,0xbb6ebb30,0x35f13705,0xbbd4bbed,0xb2a1b04e,0xbbc9bba0,0x336534d5,0xbb80bbaf,0xb593b475,
0x39723996,0x39dc39ba,0x3832385d,0x3ad03ab5,0x3927394d,0x3a1f39fe,0x37b73807,0x3b023ae9,0x38d83900,0x3a5e3a3f,0x3705375e,0x3b303b1a,0x388738b0,0x3a993a7c,0x364e36aa,0x3b5a3b46,
0x36aa3b5a,0x3b46b64e,0x38b03a99,0x3a7cb887,0xb75ebb30,0xbb1a3705,0xb900ba5e,0xba3f38d8,0x38073b02,0x3ae9b7b7,0x394d3a1f,0x39feb927,0xb85dbad0,0xbab53832,0xb996b9dc,0xb9ba3972,
0x3475bb80,0xbbafb593,0xb4d5bbc9,0xbba03365,0xb04e3bd4,0x3bed32a1,0x37053b6e,0x3b30b5f1,0xa248bbfc,0xbc00abd9,0xb887bae9,0xba993807,0x31153bf8,0x3be6ad7e,0x39723a3f,0x39dcb900,
0xbab53705,0x385d3b30,0xa2483bed,0x3c00304e,0x3972b927,0xb9dcba1f,0xb365bbf4,0xbbc92f0e,0xb7b73a7c,0x3b0238b0,0x375e3b80,0x3b1ab593,0x3414bb6e,0xbbbcb5f1,0xb94dba99,0xb9fe3887,
0x3bed34d5,0x304ebba0,0x3534bb02,0xbb91b7b7,0xbbd428b6,0x32a13bff,0x22483be6,0x3c003115,0x3ad0b5f1,0xb832bb6e,0xb593bbdd,0xbb8031db,0xb900394d,0x3a3f39fe,0x39273ae9,0x3a1fb807,
0xb94dbb02,0xb9fe37b7,0xb8d83927,0x3a5e3a1f,0x3b5a38b0,0x364eba7c,0x32a1bb46,0xbbd4b6aa,0xbbffb1db,0x28b63bdd,0x33653c00,0x3bc9a248,0x3b1ab414,0xb75ebbbc,0xb900bb30,0xba3f3705,
0x22483bbc,0x3c003414,0x3a99b534,0xb887bb91,0xb832bbaf,0xbad03475,0xb6aa3a1f,0x3b463927,0x3b1a3972,0x375eb9dc,0xaf0ebbe6,0xbbf4b115,0xbbfcb2a1,0x2bd93bd4,0x38d83b6e,0x3a5eb5f1,
0x3927b832,0xba1fbad0,0xbbafa8b6,0x34753bff,0xabd93b6e,0x3bfc35f1,0x38d8b887,0xba5eba99,0xb85dbbbc,0xbab53414,0xa2483b91,0x3c003534,0x3b803900,0x3593ba3f,0xb8b0bba0,0xba7c34d5,
0xbbe6b2a1,0x31153bd4,0x3bff364e,0x28b6bb5a,0x3900b807,0xba3fbae9,0xba1f3534,0x39273b91,0x2bd93ba0,0x3bfc34d5,0x304ebb02,0xbbedb7b7,0xb9babb46,0xb99636aa,0x38873bc9,0x3a99b365,
0x3ad03a99,0x3832b887,0xbb80b996,0xb59339ba,0xbbafb04e,0x34753bed,0x3b1aabd9,0xb75ebbfc,0x3705b927,0xbb30ba1f,0xb4143a3f,0x3bbc3900,0x35f13bff,0x3b6e28b6,0xb85dbbe6,0xbab53115,
0xb4d5bbe6,0xbba0b115,0x3a3f3b46,0x3900b6aa,0x3b9139ba,0x3534b996,0xbbbcb2a1,0x34143bd4,0xba99304e,0x38873bed,0x35f1b94d,0xbb6eb9fe,0x28b6bb02,0xbbffb7b7,0x38323bf8,0x3ad0ad7e,
0xb64e38d8,0x3b5a3a5e,0xb85dbbfc,0xbab52bd9,0xb8b0bbf4,0xba7c2f0e,0x3bff375e,0xa8b6bb1a,0x3bf836aa,0xad7ebb46,0xb7b73832,0x3b023ad0,0xb7053887,0x3b303a99,0xb807bc00,0xbae92248,
0x3b302f0e,0xb705bbf4,0x34143ba0,0x3bbc34d5,0x22483ad0,0x3c003832,0xbbddb972,0xb1db39dc,0xbb46bab5,0xb6aa385d,0x38b0b5f1,0xba7cbb6e,0x3a1fb04e,0xb927bbed,0x37b73bfc,0x3b022bd9,
0xbbbcba1f,0xb4143927,0x2bd9ba3f,0xbbfcb900,0x3887b593,0xba99bb80,0x3b5a3ad0,0x364eb832,0x38b03c00,0x3a7ca248,0xb97232a1,0x39dc3bd4,0xbbafb534,0x34753b91,0xb75ebbed,0xbb1ab04e,
0x38873bfc,0x3a992bd9,0xb5f13807,0x3b6e3ae9,0xbb80b4d5,0x35933ba0,0xba7cbbaf,0xb8b03475,0xaf0ebad0,0xbbf4b832,0x3a1fa8b6,0xb927bbff,0x3bed39ba,0x304eb996,0x37053bd4,0x3b3032a1,
0x2f0eb972,0xbbf4b9dc,0x3927b115,0xba1fbbe6,0x3bbc3a99,0x3414b887,0x394d3c00,0x39fea248,0xb64e3705,0x3b5a3b30,0xbab5b04e,0x385d3bed,0xbad0bba0,0xb83234d5,0xb6aabbaf,0xbb46b475,
0xb9dca248,0x39723c00,0xbad0b2a1,0x38323bd4,0xb927bbfc,0xba1fabd9,0xb7b7bbbc,0xbb02b414,0x3a5e2f0e,0xb8d8bbf4,0x3b3034d5,0xb705bba0,0x38873be6,0x3a993115,0x364e3b80,0x3b5a3593,
0x3bff3996,0xa8b6b9ba,0x3bc9385d,0xb365bab5,0x2d7e39fe,0x3bf8394d,0x34753ae9,0x3baf3807,0xbbedb900,0x304e3a3f,0xbb91b75e,0x35343b1a,0xb1dbba7c,0xbbddb8b0,0xb5f1bb46,0xbb6eb6aa,
0xba3fbbff,0xb90028b6,0xbbf8ba7c,0xad7e38b0,0x3807b1db,0xbae9bbdd,0xabd9b996,0xbbfcb9ba,0x3b6e3b91,0x35f1b534,0x3bd438d8,0xb2a1ba5e,0xb365375e,0x3bc93b1a,0x35933b02,0x3b8037b7,
0x31db39fe,0x3bdd394d,0x3b5a3bbc,0x364eb414,0xbb46b75e,0x36aa3b1a,0xb11537b7,0x3be63b02,0xb900bbc9,0xba3fb365,0xbbf8b9dc,0x2d7e3972,0x38d8a248,0xba5ebc00,0xb534bab5,0xbb91b85d,
0x3807ad7e,0xbae9bbf8,0xb9febbf4,0xb94daf0e,0x3bdd3b46,0x31dbb6aa,0x35f1b365,0xbb6ebbc9,0x31153996,0x3be639ba,0x3bff3ab5,0x28b6b85d,0xbb02b705,0x37b73b30,0x34d53a5e,0x3ba038d8,
0xbb91b900,0x35343a3f,0x38073b1a,0x3ae9375e,0xb996bbc9,0xb9bab365,0xb887a8b6,0x3a993bff,0x3593b2a1,0xbb80bbd4,0xbbe6bb5a,0xb115364e,0x3bf83a5e,0xad7eb8d8,0xb475b9fe,0xbbafb94d,
0x3b6e3bed,0x35f1b04e,0xb2a1b94d,0xbbd4b9fe,0x31153900,0x3be63a3f,0x39dc34d5,0xb972bba0,0xba1fb593,0x39273b80,0x3baf3bc9,0x3475b365,0xbb91bbdd,0xb53431db,0x34143996,0x3bbc39ba,
0xb75eba7c,0xbb1ab8b0,0xaf0e3593,0x3bf43b80,0x3705a248,0xbb30bc00,0xbae9b85d,0x38073ab5,0x3bdd3a5e,0xb1dbb8d8,0xbb5abbfc,0xb64e2bd9,0x39dc3baf,0x39723475,0xb365b927,0xbbc9ba1f,
0xb36531db,0x3bc93bdd,0x36aa2248,0xbb46bc00,0xbb02b8d8,0x37b73a5e,0x3ba039fe,0xb4d5b94d,0xbb91bbf8,0xb5342d7e,0x3ae93bf4,0x38072f0e,0xb64eb9dc,0xbb5ab972,0x32a138b0,0x3bd43a7c,
0x3a7c385d,0xb8b0bab5,0xb972b5f1,0x39dc3b6e,0x3bf43bbc,0x2f0eb414,0xbbf8bb30,0x2d7e3705,0x394d3b1a,0x39fe375e,0xba5ebbaf,0xb8d8b475,0xa2483593,0x3c003b80,0xb1dbb832,0xbbddbad0,
0xbbf8bbc9,0xad7e3365,0x3b023972,0xb7b7b9dc,0xb9febb5a,0xb94db64e,0x3bed3bdd,0x304eb1db,0xb2a1b807,0xbbd4bae9,0x39ba3b30,0x39963705,0x36aa2f0e,0xbb46bbf4,0x3115375e,0x3be63b1a,
0x39963ae9,0x39ba3807,0xbbddbb30,0x31db3705,0x336537b7,0x3bc93b02,0xbb80bbf8,0xb593ad7e,0xb4d5a8b6,0x3ba03bff,0xb900ba7c,0xba3fb8b0,0xb9feb85d,0x394d3ab5,0xb04eb64e,0xbbedbb5a,
0xabd9b475,0xbbfcbbaf,0x3bed3bf8,0x304ead7e,0x35f13115,0xbb6ebbe6,0x3ab53b80,0x385d3593,0x39dc3887,0xb972ba99,0x38323996,0x3ad039ba,0x3ba03ae9,0xb4d5b807,0x2f0e3534,0x3bf43b91,
0xb8d8b75e,0x3a5e3b1a,0xbb30bbaf,0xb705b475,0xbab5b9dc,0x385d3972,0xb996ba7c,0xb9bab8b0,0xbbc9bb5a,0x3365364e,0xb6aab887,0xbb46ba99,0xbbf4bbfc,0xaf0e2bd9,0xad7eb414,0xbbf8bbbc,
0x3bd43b91,0xb2a1b534,0x39ba3a5e,0x399638d8,0x3bff3bf8,0x28b6ad7e,0x38323900,0x3ad03a3f,0x3baf3be6,0x34753115,0x34d536aa,0x3ba03b46,0x3ae93b5a,0x3807364e,0x2bd931db,0x3bfc3bdd,
0xbb02bb46,0xb7b7b6aa,0xb75eb832,0xbb1abad0,0xba5ebab5,0xb8d8b85d,0xb534b64e,0xbb91bb5a,0xb996b9fe,0xb9bab94d,0xb1dbb414,0xbbddbbbc,0xb8b0b927,0xba7cba1f,0xa8b6af0e,0xbbffbbf4,
0x359335f1,0x3b803b6e,0x311531db,0x3be63bdd,0x34d53534,0x3ba03b91,0x2f0e304e,0x3bf43bed,0x34143475,0x3bbc3baf,0x2bd92d7e,0x3bfc3bf8,0x32a13365,0x3bd43bc9,0x224828b6,0x3c003bff,
0x80000,0x680060,0xc800c0,0x1280120,0xc0004,0x6c0064,0xcc00c4,0x12c0124,0x180010,0x780070,0xd800d0,0x1380130,0x1c0014,0x7c0074,0xdc00d4,0x13c0134,
0x1900188,0x1f001e8,0x2500248,0x2b002a8,0x194018c,0x1f401ec,0x254024c,0x2b402ac,0x1a00198,0x20001f8,0x2600258,0x2c002b8,0x1a4019c,0x20401fc,0x264025c,0x2c402bc,
0x3180310,0x3780370,0x3d803d0,0x4380430,0x31c0314,0x37c0374,0x3dc03d4,0x43c0434,0x3280320,0x3880380,0x3e803e0,0x4480440,0x32c0324,0x38c0384,0x3ec03e4,0x44c0444,
0x4a00498,0x50004f8,0x5600558,0x5c005b8,0x4a4049c,0x50404fc,0x564055c,0x5c405bc,0x4b004a8,0x5100508,0x5700568,0x5d005c8,0x4b404ac,0x514050c,0x574056c,0x5d405cc,
0x6280620,0x6880680,0x6e806e0,0x7480740,0x62c0624,0x68c0684,0x6ec06e4,0x74c0744,0x6380630,0x6980690,0x6f806f0,0x7580750,0x63c0634,0x69c0694,0x6fc06f4,0x75c0754,
0x7b007a8,0x8100808,0x8700868,0x8d008c8,0x7b407ac,0x814080c,0x874086c,0x8d408cc,0x7c007b8,0x8200818,0x8800878,0x8e008d8,0x7c407bc,0x824081c,0x884087c,0x8e408dc,
0x9380930,0x9980990,0x9f809f0,0xa580a50,0x93c0934,0x99c0994,0x9fc09f4,0xa5c0a54,0x9480940,0x9a809a0,0xa080a00,0xa680a60,0x94c0944,0x9ac09a4,0xa0c0a04,0xa6c0a64,
0xac00ab8,0xb200b18,0xb800b78,0xbe00bd8,0xac40abc,0xb240b1c,0xb840b7c,0xbe40bdc,0xad00ac8,0xb300b28,0xb900b88,0xbf00be8,0xad40acc,0xb340b2c,0xb940b8c,0xbf40bec,
0x280020,0x880080,0xe800e0,0x1480140,0x2c0024,0x8c0084,0xec00e4,0x14c0144,0x240020,0x840080,0xe400e0,0x1440140,0x800024,0xe00084,0x14000e4,0x1a80144,
0x1b001a8,0x2100208,0x2700268,0x2d002c8,0x1b401ac,0x214020c,0x274026c,0x2d402cc,0x1ac01a8,0x20c0208,0x26c0268,0x2cc02c8,0x20801ac,0x268020c,0x2c8026c,0x33002cc,
0x3380330,0x3980390,0x3f803f0,0x4580450,0x33c0334,0x39c0394,0x3fc03f4,0x45c0454,0x3340330,0x3940390,0x3f403f0,0x4540450,0x3900334,0x3f00394,0x45003f4,0x4b80454,
0x4c004b8,0x5200518,0x5800578,0x5e005d8,0x4c404bc,0x524051c,0x584057c,0x5e405dc,0x4bc04b8,0x51c0518,0x57c0578,0x5dc05d8,0x51804bc,0x578051c,0x5d8057c,0x64005dc,
0x6480640,0x6a806a0,0x7080700,0x7680760,0x64c0644,0x6ac06a4,0x70c0704,0x76c0764,0x6440640,0x6a406a0,0x7040700,0x7640760,0x6a00644,0x70006a4,0x7600704,0x7c80764,
0x7d007c8,0x8300828,0x8900888,0x8f008e8,0x7d407cc,0x834082c,0x894088c,0x8f408ec,0x7cc07c8,0x82c0828,0x88c0888,0x8ec08e8,0x82807cc,0x888082c,0x8e8088c,0x95008ec,
0x9580950,0x9b809b0,0xa180a10,0xa780a70,0x95c0954,0x9bc09b4,0xa1c0a14,0xa7c0a74,0x9540950,0x9b409b0,0xa140a10,0xa740a70,0x9b00954,0xa1009b4,0xa700a14,0xad80a74,
0xae00ad8,0xb400b38,0xba00b98,0xc000bf8,0xae40adc,0xb440b3c,0xba40b9c,0xc040bfc,0xadc0ad8,0xb3c0b38,0xb9c0b98,0xbfc0bf8,0xb380adc,0xb980b3c,0xbf80b9c,0x300bfc,
0x300030,0x900090,0xf000f0,0x1500150,0x900034,0xf00094,0x15000f4,0x1b80154,0x340030,0x940090,0xf400f0,0x1540150,0x900034,0xf00094,0x15000f4,0x1b80154,
0x1b801b8,0x2180218,0x2780278,0x2d802d8,0x21801bc,0x278021c,0x2d8027c,0x34002dc,0x1bc01b8,0x21c0218,0x27c0278,0x2dc02d8,0x21801bc,0x278021c,0x2d8027c,0x34002dc,
0x3400340,0x3a003a0,0x4000400,0x4600460,0x3a00344,0x40003a4,0x4600404,0x4c80464,0x3440340,0x3a403a0,0x4040400,0x4640460,0x3a00344,0x40003a4,0x4600404,0x4c80464,
0x4c804c8,0x5280528,0x5880588,0x5e805e8,0x52804cc,0x588052c,0x5e8058c,0x65005ec,0x4cc04c8,0x52c0528,0x58c0588,0x5ec05e8,0x52804cc,0x588052c,0x5e8058c,0x65005ec,
0x6500650,0x6b006b0,0x7100710,0x7700770,0x6b00654,0x71006b4,0x7700714,0x7d80774,0x6540650,0x6b406b0,0x7140710,0x7740770,0x6b00654,0x71006b4,0x7700714,0x7d80774,
0x7d807d8,0x8380838,0x8980898,0x8f808f8,0x83807dc,0x898083c,0x8f8089c,0x96008fc,0x7dc07d8,0x83c0838,0x89c0898,0x8fc08f8,0x83807dc,0x898083c,0x8f8089c,0x96008fc,
0x9600960,0x9c009c0,0xa200a20,0xa800a80,0x9c00964,0xa2009c4,0xa800a24,0xae80a84,0x9640960,0x9c409c0,0xa240a20,0xa840a80,0x9c00964,0xa2009c4,0xa800a24,0xae80a84,
0xae80ae8,0xb480b48,0xba80ba8,0xc080c08,0xb480aec,0xba80b4c,0xc080bac,0x380c0c,0xaec0ae8,0xb4c0b48,0xbac0ba8,0xc0c0c08,0xb480aec,0xba80b4c,0xc080bac,0x380c0c,
0x380038,0x980098,0xf800f8,0x1580158,0x98003c,0xf8009c,0x15800fc,0x1c0015c,0x3c0038,0x9c0098,0xfc00f8,0x15c0158,0x98003c,0xf8009c,0x15800fc,0x1c0015c,
0x1c001c0,0x2200220,0x2800280,0x2e002e0,0x22001c4,0x2800224,0x2e00284,0x34802e4,0x1c401c0,0x2240220,0x2840280,0x2e402e0,0x22001c4,0x2800224,0x2e00284,0x34802e4,
0x3480348,0x3a803a8,0x4080408,0x4680468,0x3a8034c,0x40803ac,0x468040c,0x4d0046c,0x34c0348,0x3ac03a8,0x40c0408,0x46c0468,0x3a8034c,0x40803ac,0x468040c,0x4d0046c,
0x4d004d0,0x5300530,0x5900590,0x5f005f0,0x53004d4,0x5900534,0x5f00594,0x65805f4,0x4d404d0,0x5340530,0x5940590,0x5f405f0,0x53004d4,0x5900534,0x5f00594,0x65805f4,
0x6580658,0x6b806b8,0x7180718,0x7780778,0x6b8065c,0x71806bc,0x778071c,0x7e0077c,0x65c0658,0x6bc06b8,0x71c0718,0x77c0778,0x6b8065c,0x71806bc,0x778071c,0x7e0077c,
0x7e007e0,0x8400840,0x8a008a0,0x9000900,0x84007e4,0x8a00844,0x90008a4,0x9680904,0x7e407e0,0x8440840,0x8a408a0,0x9040900,0x84007e4,0x8a00844,0x90008a4,0x9680904,
0x9680968,0x9c809c8,0xa280a28,0xa880a88,0x9c8096c,0xa2809cc,0xa880a2c,0xaf00a8c,0x96c0968,0x9cc09c8,0xa2c0a28,0xa8c0a88,0x9c8096c,0xa2809cc,0xa880a2c,0xaf00a8c,
0xaf00af0,0xb500b50,0xbb00bb0,0xc100c10,0xb500af4,0xbb00b54,0xc100bb4,0x400c14,0xaf40af0,0xb540b50,0xbb40bb0,0xc140c10,0xb500af4,0xbb00b54,0xc100bb4,0x400c14,
0xb040b04,0xb640b64,0xbc40bc4,0xc240c24,0xb640b04,0xbc40bc4,0xc240bc4,0x500050,0xb040b04,0xb640b64,0xbc40bc4,0xc240c24,0xb640b64,0xbc40bc4,0xc240c24,0x500050,
0x97c097c,0x9dc09dc,0xa3c0a3c,0xa9c0a9c,0x9dc097c,0xa3c0a3c,0xa9c0a3c,0xb040b04,0x97c097c,0x9dc09dc,0xa3c0a3c,0xa9c0a9c,0x9dc09dc,0xa3c0a3c,0xa9c0a9c,0xb040b04,
0x7f407f4,0x8540854,0x8b408b4,0x9140914,0x85407f4,0x8b408b4,0x91408b4,0x97c097c,0x7f407f4,0x8540854,0x8b408b4,0x9140914,0x8540854,0x8b408b4,0x9140914,0x97c097c,
0x66c066c,0x6cc06cc,0x72c072c,0x78c078c,0x6cc066c,0x72c072c,0x78c072c,0x7f407f4,0x66c066c,0x6cc06cc,0x72c072c,0x78c078c,0x6cc06cc,0x72c072c,0x78c078c,0x7f407f4,
0x4e404e4,0x5440544,0x5a405a4,0x6040604,0x54404e4,0x5a405a4,0x60405a4,0x66c066c,0x4e404e4,0x5440544,0x5a405a4,0x6040604,0x5440544,0x5a405a4,0x6040604,0x66c066c,
0x35c035c,0x3bc03bc,0x41c041c,0x47c047c,0x3bc035c,0x41c041c,0x47c041c,0x4e404e4,0x35c035c,0x3bc03bc,0x41c041c,0x47c047c,0x3bc03bc,0x41c041c,0x47c047c,0x4e404e4,
0x1d401d4,0x2340234,0x2940294,0x2f402f4,0x23401d4,0x2940294,0x2f40294,0x35c035c,0x1d401d4,0x2340234,0x2940294,0x2f402f4,0x2340234,0x2940294,0x2f402f4,0x35c035c,
0x4c004c,0xac00ac,0x10c010c,0x16c016c,0xac004c,0x10c010c,0x16c010c,0x1d401d4,0x4c004c,0xac00ac,0x10c010c,0x16c016c,0xac00ac,0x10c010c,0x16c016c,0x1d401d4,
0xb000b00,0xb600b60,0xbc00bc0,0xc200c20,0xb600b00,0xbc00bc0,0xc200bc0,0x4c004c,0xb000b00,0xb600b60,0xbc00bc0,0xc200c20,0xb600b60,0xbc00bc0,0xc200c20,0x4c004c,
0x9780978,0x9d809d8,0xa380a38,0xa980a98,0x9d80978,0xa380a38,0xa980a38,0xb000b00,0x9780978,0x9d809d8,0xa380a38,0xa980a98,0x9d809d8,0xa380a38,0xa980a98,0xb000b00,
0x7f007f0,0x8500850,0x8b008b0,0x9100910,0x85007f0,0x8b008b0,0x91008b0,0x9780978,0x7f007f0,0x8500850,0x8b008b0,0x9100910,0x8500850,0x8b008b0,0x9100910,0x9780978,
0x6680668,0x6c806c8,0x7280728,0x7880788,0x6c80668,0x7280728,0x7880728,0x7f007f0,0x6680668,0x6c806c8,0x7280728,0x7880788,0x6c806c8,0x7280728,0x7880788,0x7f007f0,
0x4e004e0,0x5400540,0x5a005a0,0x6000600,0x54004e0,0x5a005a0,0x60005a0,0x6680668,0x4e004e0,0x5400540,0x5a005a0,0x6000600,0x5400540,0x5a005a0,0x6000600,0x6680668,
0x3580358,0x3b803b8,0x4180418,0x4780478,0x3b80358,0x4180418,0x4780418,0x4e004e0,0x3580358,0x3b803b8,0x4180418,0x4780478,0x3b803b8,0x4180418,0x4780478,0x4e004e0,
0x1d001d0,0x2300230,0x2900290,0x2f002f0,0x23001d0,0x2900290,0x2f00290,0x3580358,0x1d001d0,0x2300230,0x2900290,0x2f002f0,0x2300230,0x2900290,0x2f002f0,0x3580358,
0x480048,0xa800a8,0x1080108,0x1680168,0xa80048,0x1080108,0x1680108,0x1d001d0,0x480048,0xa800a8,0x1080108,0x1680168,0xa800a8,0x1080108,0x1680168,0x1d001d0,
0xafc0afc,0xb5c0b5c,0xbbc0bbc,0xc1c0c1c,0xb5c0afc,0xbbc0bbc,0xc1c0bbc,0x480048,0xafc0afc,0xb5c0b5c,0xbbc0bbc,0xc1c0c1c,0xb5c0b5c,0xbbc0bbc,0xc1c0c1c,0x480048,
0x9740974,0x9d409d4,0xa340a34,0xa940a94,0x9d40974,0xa340a34,0xa940a34,0xafc0afc,0x9740974,0x9d409d4,0xa340a34,0xa940a94,0x9d409d4,0xa340a34,0xa940a94,0xafc0afc,
0x7ec07ec,0x84c084c,0x8ac08ac,0x90c090c,0x84c07ec,0x8ac08ac,0x90c08ac,0x9740974,0x7ec07ec,0x84c084c,0x8ac08ac,0x90c090c,0x84c084c,0x8ac08ac,0x90c090c,0x9740974,
0x6640664,0x6c406c4,0x7240724,0x7840784,0x6c40664,0x7240724,0x7840724,0x7ec07ec,0x6640664,0x6c406c4,0x7240724,0x7840784,0x6c406c4,0x7240724,0x7840784,0x7ec07ec,
0x4dc04dc,0x53c053c,0x59c059c,0x5fc05fc,0x53c04dc,0x59c059c,0x5fc059c,0x6640664,0x4dc04dc,0x53c053c,0x59c059c,0x5fc05fc,0x53c053c,0x59c059c,0x5fc05fc,0x6640664,
0x3540354,0x3b403b4,0x4140414,0x4740474,0x3b40354,0x4140414,0x4740414,0x4dc04dc,0x3540354,0x3b403b4,0x4140414,0x4740474,0x3b403b4,0x4140414,0x4740474,0x4dc04dc,
0x1cc01cc,0x22c022c,0x28c028c,0x2ec02ec,0x22c01cc,0x28c028c,0x2ec028c,0x3540354,0x1cc01cc,0x22c022c,0x28c028c,0x2ec02ec,0x22c022c,0x28c028c,0x2ec02ec,0x3540354,
0x440044,0xa400a4,0x1040104,0x1640164,0xa40044,0x1040104,0x1640104,0x1cc01cc,0x440044,0xa400a4,0x1040104,0x1640164,0xa400a4,0x1040104,0x1640164,0x1cc01cc,
0xaf80af8,0xb580b58,0xbb80bb8,0xc180c18,0xb580af8,0xbb80bb8,0xc180bb8,0x440044,0xaf80af8,0xb580b58,0xbb80bb8,0xc180c18,0xb580b58,0xbb80bb8,0xc180c18,0x440044,
0x9700970,0x9d009d0,0xa300a30,0xa900a90,0x9d00970,0xa300a30,0xa900a30,0xaf80af8,0x9700970,0x9d009d0,0xa300a30,0xa900a90,0x9d009d0,0xa300a30,0xa900a90,0xaf80af8,
0x7e807e8,0x8480848,0x8a808a8,0x9080908,0x84807e8,0x8a808a8,0x90808a8,0x9700970,0x7e807e8,0x8480848,0x8a808a8,0x9080908,0x8480848,0x8a808a8,0x9080908,0x9700970,
0x6600660,0x6c006c0,0x7200720,0x7800780,0x6c00660,0x7200720,0x7800720,0x7e807e8,0x6600660,0x6c006c0,0x7200720,0x7800780,0x6c006c0,0x7200720,0x7800780,0x7e807e8,
0x4d804d8,0x5380538,0x5980598,0x5f805f8,0x53804d8,0x5980598,0x5f80598,0x6600660,0x4d804d8,0x5380538,0x5980598,0x5f805f8,0x5380538,0x5980598,0x5f805f8,0x6600660,
0x3500350,0x3b003b0,0x4100410,0x4700470,0x3b00350,0x4100410,0x4700410,0x4d804d8,0x3500350,0x3b003b0,0x4100410,0x4700470,0x3b003b0,0x4100410,0x4700470,0x4d804d8,
0x1c801c8,0x2280228,0x2880288,0x2e802e8,0x22801c8,0x2880288,0x2e80288,0x3500350,0x1c801c8,0x2280228,0x2880288,0x2e802e8,0x2280228,0x2880288,0x2e802e8,0x3500350,
0x400040,0xa000a0,0x1000100,0x1600160,0xa00040,0x1000100,0x1600100,0x1c801c8,0x400040,0xa000a0,0x1000100,0x1600160,0xa000a0,0x1000100,0x1600160,0x1c801c8,
0x30003000,0x30003000,0x30003000,0x30003000,0x30003000,0x30003000,0x30003000,0x30003000,0x0,0x0,0x0,0x0,0x0,0x0,0x0,0x0,
0x30003000,0x30003000,0x30003000,0x30003000,0x30003000,0x30003000,0x30003000,0x30003000,0x0,0x0,0x0,0x0,0x0,0x0,0x0,0x0,
0x2a1f2da8,0xaf64ada8,0xaa1fada8,0x2f642da8,0x2f643000,0xaa1f0000,0xaf64b000,0x2a1f8000,0x2f642da8,0x2a1f2da8,0xaf64ada8,0xaa1fada8,0x2a1f0000,0x2f643000,0xaa1f0000,0xaf64b000,
0x263e2c72,0xafd9aea7,0xa63eac72,0x2fd92ea7,0x2ea72fd9,0xac72a63e,0xaea7afd9,0x2c72263e,0x2fd92ea7,0x263e2c72,0xafd9aea7,0xa63eac72,0x2c72263e,0x2ea72fd9,0xac72a63e,0xaea7afd9,
0x2da80000,0xada80000,0x2da88000,0xada80000,0x2da83000,0xada8b000,0x2da83000,0xada8b000,0x2da83000,0xada8b000,0x2da83000,0xada8b000,0xada80000,0x2da88000,0xada80000,0x2da88000,
0x2f642a1f,0xaf64aa1f,0x2f642a1f,0xaf64aa1f,0x2a1f2f64,0xaa1faf64,0x2a1f2f64,0xaa1faf64,0x2a1f2f64,0xaa1faf64,0x2a1f2f64,0xaa1faf64,0xaf64aa1f,0x2f642a1f,0xaf64aa1f,0x2f642a1f,
0xaa1f2da8,0x2f642da8,0x2a1fada8,0xaf64ada8,0x2f640000,0xaa1fb000,0xaf640000,0x2a1f3000,0xaf64ada8,0xaa1f2da8,0x2f642da8,0x2a1fada8,0x2a1f3000,0x2f648000,0xaa1fb000,0xaf640000,
0xaea7263e,0x2c722fd9,0x2ea7a63e,0xac72afd9,0x2fd92c72,0x263eaea7,0xafd9ac72,0xa63e2ea7,0xac72afd9,0xaea7263e,0x2c722fd9,0x2ea7a63e,0xa63e2ea7,0x2fd92c72,0x263eaea7,0xafd9ac72,
0xada82da8,0xada82da8,0xada82da8,0xada82da8,0x2da8ada8,0x2da8ada8,0x2da8ada8,0x2da8ada8,0x2da82da8,0x2da82da8,0x2da82da8,0x2da82da8,0xada8ada8,0xada8ada8,0xada8ada8,0xada8ada8,
0x3000,0x3000,0x3000,0x80003000,0x8000b000,0x8000b000,0x8000b000,0x8000b000,0x30000000,0x30008000,0x30008000,0x30008000,0xb0000000,0xb0000000,0xb0000000,0xb0000000,
0x2ea7263e,0xac722fd9,0xaea7a63e,0x2c72afd9,0xafd92c72,0xa63eaea7,0x2fd9ac72,0x263e2ea7,0x2c72afd9,0x2ea7263e,0xac722fd9,0xaea7a63e,0x263e2ea7,0xafd92c72,0xa63eaea7,0x2fd9ac72,
0x2f64ada8,0x2a1f2da8,0xaf642da8,0xaa1fada8,0xaa1f3000,0xaf640000,0x2a1fb000,0x2f648000,0xaa1fada8,0x2f64ada8,0x2a1f2da8,0xaf642da8,0x2f640000,0xaa1f3000,0xaf640000,0x2a1fb000,
0xaa1f2f64,0x2a1faf64,0xaa1f2f64,0x2a1faf64,0x2f64aa1f,0xaf642a1f,0x2f64aa1f,0xaf642a1f,0xaf642a1f,0x2f64aa1f,0xaf642a1f,0x2f64aa1f,0xaa1f2f64,0x2a1faf64,0xaa1f2f64,0x2a1faf64,
0x2da80000,0xada80000,0x2da88000,0xada80000,0x2da8b000,0xada83000,0x2da8b000,0xada83000,0xada83000,0x2da8b000,0xada83000,0x2da8b000,0x2da88000,0xada80000,0x2da88000,0xada88000,
0xa63e2c72,0x2fd9aea7,0x263eac72,0xafd92ea7,0xaea72fd9,0x2c72a63e,0x2ea7afd9,0xac72263e,0xafd92ea7,0xa63e2c72,0x2fd9aea7,0x263eac72,0xac72263e,0xaea72fd9,0x2c72a63e,0x2ea7afd9,
0x2f64ada8,0x2a1fada8,0xaf642da8,0xaa1f2da8,0x2a1f0000,0x2f64b000,0xaa1f0000,0xaf643000,0xaa1f2da8,0x2f64ada8,0x2a1fada8,0xaf642da8,0xaf643000,0x2a1f8000,0x2f64b000,0xaa1f8000,
0xb0003000,0xb0003000,0xb0003000,0xb0003000,0xb0003000,0xb0003000,0xb0003000,0xb0003000,0x0,0x8000,0x8000,0x80008000,0x8000,0x8000,0x8000,0x8000,
0x80000000,0x80000000,0x80008000,0x80008000,0x80000000,0x80008000,0x80008000,0x80008000,0xb0003000,0xb0003000,0xb0003000,0xb0003000,0xb0003000,0xb0003000,0xb0003000,0xb0003000,
0xaa1f2da8,0x2f64ada8,0x2a1fada8,0xaf642da8,0xaf643000,0x2a1f0000,0x2f64b000,0xaa1f8000,0xaf642da8,0xaa1f2da8,0x2f64ada8,0x2a1fada8,0xaa1f0000,0xaf643000,0x2a1f0000,0x2f64b000,
0x2fd9aea7,0x263eac72,0xafd92ea7,0xa63e2c72,0x2c72a63e,0x2ea7afd9,0xac72263e,0xaea72fd9,0xa63e2c72,0x2fd9aea7,0x263eac72,0xafd92ea7,0xaea72fd9,0x2c72a63e,0x2ea7afd9,0xac72263e,
0xada80000,0x2da80000,0xada88000,0x2da80000,0xada83000,0x2da8b000,0xada83000,0x2da8b000,0xada83000,0x2da8b000,0xada83000,0x2da8b000,0x2da80000,0xada88000,0x2da88000,0xada88000,
0xaa1f2f64,0x2a1faf64,0xaa1f2f64,0x2a1faf64,0x2f64aa1f,0xaf642a1f,0x2f64aa1f,0xaf642a1f,0x2f64aa1f,0xaf642a1f,0x2f64aa1f,0xaf642a1f,0x2a1faf64,0xaa1f2f64,0x2a1faf64,0xaa1f2f64,
0x2a1f2da8,0xaf642da8,0xaa1fada8,0x2f64ada8,0xaf640000,0x2a1fb000,0x2f640000,0xaa1f3000,0x2f64ada8,0x2a1f2da8,0xaf642da8,0xaa1fada8,0xaa1f3000,0xaf648000,0x2a1fb000,0x2f640000,
0x2c72afd9,0x2ea7263e,0xac722fd9,0xaea7a63e,0x263e2ea7,0xafd92c72,0xa63eaea7,0x2fd9ac72,0xaea7a63e,0x2c72afd9,0x2ea7263e,0xac722fd9,0x2fd9ac72,0x263e2ea7,0xafd92c72,0xa63eaea7,
0x2da8ada8,0x2da8ada8,0x2da8ada8,0x2da8ada8,0xada82da8,0xada82da8,0xada82da8,0xada82da8,0x2da82da8,0x2da82da8,0x2da82da8,0x2da82da8,0xada8ada8,0xada8ada8,0xada8ada8,0xada8ada8,
0x80003000,0x80003000,0x80003000,0x3000,0xb000,0x8000b000,0xb000,0xb000,0xb0000000,0xb0008000,0xb0008000,0xb0008000,0x30000000,0x30000000,0x30000000,0x30008000,
0x2c722fd9,0x2ea7a63e,0xac72afd9,0xaea7263e,0x263eaea7,0xafd9ac72,0xa63e2ea7,0x2fd92c72,0xaea7263e,0x2c722fd9,0x2ea7a63e,0xac72afd9,0x2fd92c72,0x263eaea7,0xafd9ac72,0xa63e2ea7,
0xaf64ada8,0xaa1f2da8,0x2f642da8,0x2a1fada8,0x2a1f3000,0x2f648000,0xaa1fb000,0xaf648000,0x2a1fada8,0xaf64ada8,0xaa1f2da8,0x2f642da8,0xaf640000,0x2a1f3000,0x2f648000,0xaa1fb000,
0x2f642a1f,0xaf64aa1f,0x2f642a1f,0xaf64aa1f,0x2a1f2f64,0xaa1faf64,0x2a1f2f64,0xaa1faf64,0xaa1faf64,0x2a1f2f64,0xaa1faf64,0x2a1f2f64,0x2f642a1f,0xaf64aa1f,0x2f642a1f,0xaf64aa1f,
0xada80000,0x2da80000,0xada88000,0x2da88000,0xada8b000,0x2da83000,0xada8b000,0x2da83000,0x2da83000,0xada8b000,0x2da83000,0xada8b000,0xada88000,0x2da88000,0xada88000,0x2da80000,
0x2fd92ea7,0x263e2c72,0xafd9aea7,0xa63eac72,0x2c72263e,0x2ea72fd9,0xac72a63e,0xaea7afd9,0xa63eac72,0x2fd92ea7,0x263e2c72,0xafd9aea7,0xaea7afd9,0x2c72263e,0x2ea72fd9,0xac72a63e,
0xaf64ada8,0xaa1fada8,0x2f642da8,0x2a1f2da8,0xaa1f0000,0xaf64b000,0x2a1f0000,0x2f643000,0x2a1f2da8,0xaf64ada8,0xaa1fada8,0x2f642da8,0x2f643000,0xaa1f8000,0xaf64b000,0x2a1f0000,
0x80008000,0x80008000,0x80008000,0x80008000,0x80008000,0x80008000,0x80008000,0x80008000,0x30003000,0x30003000,0x30003000,0x30003000,0x30003000,0x30003000,0x30003000,0x30003000,
0x80008000,0x80008000,0x80008000,0x80008000,0x80008000,0x80008000,0x80008000,0x80008000,0x30003000,0x30003000,0x30003000,0x30003000,0x30003000,0x30003000,0x30003000,0x30003000,
0xaf64ada8,0xaa1fada8,0x2f642da8,0x2a1f2da8,0xaa1f8000,0xaf64b000,0x2a1f8000,0x2f643000,0x2a1f2da8,0xaf64ada8,0xaa1fada8,0x2f642da8,0x2f643000,0xaa1f0000,0xaf64b000,0x2a1f8000,
0xafd9aea7,0xa63eac72,0x2fd92ea7,0x263e2c72,0xac72a63e,0xaea7afd9,0x2c72263e,0x2ea72fd9,0x263e2c72,0xafd9aea7,0xa63eac72,0x2fd92ea7,0x2ea72fd9,0xac72a63e,0xaea7afd9,0x2c72263e,
0x2da83000,0xada8b000,0x2da83000,0xada8b000,0xada80000,0x2da88000,0xada80000,0x2da88000,0xada88000,0x2da88000,0xada80000,0x2da88000,0xada8b000,0x2da83000,0xada8b000,0x2da83000,
0x2a1f2f64,0xaa1faf64,0x2a1f2f64,0xaa1faf64,0xaf64aa1f,0x2f642a1f,0xaf64aa1f,0x2f642a1f,0xaf64aa1f,0x2f642a1f,0xaf64aa1f,0x2f642a1f,0xaa1faf64,0x2a1f2f64,0xaa1faf64,0x2a1f2f64,
0xaf64ada8,0xaa1f2da8,0x2f642da8,0x2a1fada8,0x2a1f3000,0x2f648000,0xaa1fb000,0xaf640000,0x2a1fada8,0xaf64ada8,0xaa1f2da8,0x2f642da8,0xaf648000,0x2a1f3000,0x2f648000,0xaa1fb000,
0xac72afd9,0xaea7263e,0x2c722fd9,0x2ea7a63e,0xa63e2ea7,0x2fd92c72,0x263eaea7,0xafd9ac72,0x2ea7a63e,0xac72afd9,0xaea7263e,0x2c722fd9,0xafd9ac72,0xa63e2ea7,0x2fd92c72,0x263eaea7,
0xada8ada8,0xada8ada8,0xada8ada8,0xada8ada8,0x2da82da8,0x2da82da8,0x2da82da8,0x2da82da8,0xada82da8,0xada82da8,0xada82da8,0xada82da8,0x2da8ada8,0x2da8ada8,0x2da8ada8,0x2da8ada8,
0xb0008000,0xb0000000,0xb0000000,0xb0000000,0x30008000,0x30008000,0x30008000,0x30008000,0x3000,0x3000,0x3000,0x80003000,0x8000b000,0x8000b000,0x8000b000,0x8000b000,
0xac722fd9,0xaea7a63e,0x2c72afd9,0x2ea7263e,0xa63eaea7,0x2fd9ac72,0x263e2ea7,0xafd92c72,0x2ea7263e,0xac722fd9,0xaea7a63e,0x2c72afd9,0xafd92c72,0xa63eaea7,0x2fd9ac72,0x263e2ea7,
0x2a1f2da8,0xaf642da8,0xaa1fada8,0x2f64ada8,0xaf648000,0x2a1fb000,0x2f648000,0xaa1f3000,0x2f64ada8,0x2a1f2da8,0xaf642da8,0xaa1fada8,0xaa1f3000,0xaf640000,0x2a1fb000,0x2f648000,
0xaf642a1f,0x2f64aa1f,0xaf642a1f,0x2f64aa1f,0xaa1f2f64,0x2a1faf64,0xaa1f2f64,0x2a1faf64,0x2a1faf64,0xaa1f2f64,0x2a1faf64,0xaa1f2f64,0xaf642a1f,0x2f64aa1f,0xaf642a1f,0x2f64aa1f,
0xada83000,0x2da8b000,0xada83000,0x2da8b000,0x2da88000,0xada80000,0x2da88000,0xada88000,0xada88000,0x2da88000,0xada80000,0x2da88000,0xada83000,0x2da8b000,0xada83000,0x2da8b000,
0xafd92ea7,0xa63e2c72,0x2fd9aea7,0x263eac72,0xac72263e,0xaea72fd9,0x2c72a63e,0x2ea7afd9,0x263eac72,0xafd92ea7,0xa63e2c72,0x2fd9aea7,0x2ea7afd9,0xac72263e,0xaea72fd9,0x2c72a63e,
0xaa1f2da8,0x2f64ada8,0x2a1fada8,0xaf642da8,0xaf643000,0x2a1f8000,0x2f64b000,0xaa1f8000,0xaf642da8,0xaa1f2da8,0x2f64ada8,0x2a1fada8,0xaa1f8000,0xaf643000,0x2a1f8000,0x2f64b000,
0x80008000,0x80000000,0x80000000,0x0,0x80000000,0x80000000,0x80000000,0x80000000,0xb0003000,0xb0003000,0xb0003000,0xb0003000,0xb0003000,0xb0003000,0xb0003000,0xb0003000,
0x3000b000,0x3000b000,0x3000b000,0x3000b000,0x3000b000,0x3000b000,0x3000b000,0x3000b000,0x80000000,0x80000000,0x80008000,0x80008000,0x80000000,0x80008000,0x80008000,0x80008000,
0x2f64ada8,0x2a1fada8,0xaf642da8,0xaa1f2da8,0x2a1f8000,0x2f64b000,0xaa1f8000,0xaf643000,0xaa1f2da8,0x2f64ada8,0x2a1fada8,0xaf642da8,0xaf643000,0x2a1f0000,0x2f64b000,0xaa1f8000,
0x263eac72,0xafd92ea7,0xa63e2c72,0x2fd9aea7,0x2ea7afd9,0xac72263e,0xaea72fd9,0x2c72a63e,0x2fd9aea7,0x263eac72,0xafd92ea7,0xa63e2c72,0x2c72a63e,0x2ea7afd9,0xac72263e,0xaea72fd9,
0xada83000,0x2da8b000,0xada83000,0x2da8b000,0x2da80000,0xada88000,0x2da88000,0xada88000,0x2da88000,0xada88000,0x2da80000,0xada88000,0x2da8b000,0xada83000,0x2da8b000,0xada83000,
0x2f64aa1f,0xaf642a1f,0x2f64aa1f,0xaf642a1f,0x2a1faf64,0xaa1f2f64,0x2a1faf64,0xaa1f2f64,0x2a1faf64,0xaa1f2f64,0x2a1faf64,0xaa1f2f64,0xaf642a1f,0x2f64aa1f,0xaf642a1f,0x2f64aa1f,
0x2f64ada8,0x2a1f2da8,0xaf642da8,0xaa1fada8,0xaa1f3000,0xaf648000,0x2a1fb000,0x2f640000,0xaa1fada8,0x2f64ada8,0x2a1f2da8,0xaf642da8,0x2f648000,0xaa1f3000,0xaf648000,0x2a1fb000,
0xaea7a63e,0x2c72afd9,0x2ea7263e,0xac722fd9,0x2fd9ac72,0x263e2ea7,0xafd92c72,0xa63eaea7,0xac722fd9,0xaea7a63e,0x2c72afd9,0x2ea7263e,0xa63eaea7,0x2fd9ac72,0x263e2ea7,0xafd92c72,
0xada8ada8,0xada8ada8,0xada8ada8,0xada8ada8,0x2da82da8,0x2da82da8,0x2da82da8,0x2da82da8,0x2da8ada8,0x2da8ada8,0x2da8ada8,0x2da8ada8,0xada82da8,0xada82da8,0xada82da8,0xada82da8,
0x30008000,0x30000000,0x30000000,0x30000000,0xb0008000,0xb0008000,0xb0008000,0xb0000000,0x80003000,0x80003000,0x80003000,0x3000,0xb000,0x8000b000,0xb000,0xb000,
0x2ea7a63e,0xac72afd9,0xaea7263e,0x2c722fd9,0xafd9ac72,0xa63e2ea7,0x2fd92c72,0x263eaea7,0x2c722fd9,0x2ea7a63e,0xac72afd9,0xaea7263e,0x263eaea7,0xafd9ac72,0xa63e2ea7,0x2fd92c72,
0xaa1f2da8,0x2f642da8,0x2a1fada8,0xaf64ada8,0x2f648000,0xaa1fb000,0xaf640000,0x2a1f3000,0xaf64ada8,0xaa1f2da8,0x2f642da8,0x2a1fada8,0x2a1f3000,0x2f648000,0xaa1fb000,0xaf648000,
0xaa1faf64,0x2a1f2f64,0xaa1faf64,0x2a1f2f64,0x2f642a1f,0xaf64aa1f,0x2f642a1f,0xaf64aa1f,0xaf64aa1f,0x2f642a1f,0xaf64aa1f,0x2f642a1f,0xaa1faf64,0x2a1f2f64,0xaa1faf64,0x2a1f2f64,
0x2da83000,0xada8b000,0x2da83000,0xada8b000,0xada88000,0x2da88000,0xada88000,0x2da80000,0x2da88000,0xada88000,0x2da80000,0xada80000,0x2da83000,0xada8b000,0x2da83000,0xada8b000,
0xa63eac72,0x2fd92ea7,0x263e2c72,0xafd9aea7,0xaea7afd9,0x2c72263e,0x2ea72fd9,0xac72a63e,0xafd9aea7,0xa63eac72,0x2fd92ea7,0x263e2c72,0xac72a63e,0xaea7afd9,0x2c72263e,0x2ea72fd9,
0x2a1f2da8,0xaf64ada8,0xaa1fada8,0x2f642da8,0x2f643000,0xaa1f8000,0xaf64b000,0x2a1f0000,0x2f642da8,0x2a1f2da8,0xaf64ada8,0xaa1fada8,0x2a1f8000,0x2f643000,0xaa1f8000,0xaf64b000,
0x3c003c00,0x3c003c00,0x3c003c00,0x3c003c00,0x3c003c00,0x3c003c00,0x3c003c00,0x3c003c00,0x80008000,0x80008000,0x80008000,0x80008000,0x80008000,0x80008000,0x80008000,0x80008000,
0x3bd93c00,0x3aa73b64,0x387239a8,0x323e361f,0xb23e0000,0xb872b61f,0xbaa7b9a8,0xbbd9bb64,0xb23e8000,0xb872b61f,0xbaa7b9a8,0xbbd9bb64,0xbbd9bc00,0xbaa7bb64,0xb872b9a8,0xb23eb61f,
0xbb64bc00,0xb61fb9a8,0x361f8000,0x3b6439a8,0x3b643c00,0x361f39a8,0xb61f0000,0xbb64b9a8,0x361f8000,0x3b6439a8,0x3b643c00,0x361f39a8,0xb61f8000,0xbb64b9a8,0xbb64bc00,0xb61fb9a8,
0x38728000,0x3bd93b64,0x323e39a8,0xbaa7b61f,0x3aa73c00,0xb23e361f,0xbbd9b9a8,0xb872bb64,0x3aa73c00,0xb23e361f,0xbbd9b9a8,0xb872bb64,0xb8728000,0xbbd9bb64,0xb23eb9a8,0x3aa7361f,
0xbc008000,0x3c008000,0xbc000000,0x3c008000,0xbc000000,0x3c008000,0xbc000000,0x3c008000,0x3c00,0x8000bc00,0x3c00,0x8000bc00,0x3c00,0x8000bc00,0x80003c00,0x8000bc00,
0xbbd98000,0x3aa7361f,0xb872b9a8,0x323e3b64,0x323ebc00,0xb8723b64,0x3aa7b9a8,0xbbd9361f,0xb23e3c00,0x3872bb64,0xbaa739a8,0x3bd9b61f,0xbbd90000,0x3aa7361f,0xb872b9a8,0x323e3b64,
0x3b648000,0xb61fb9a8,0xb61f3c00,0x3b64b9a8,0xbb648000,0x361f39a8,0x361fbc00,0xbb6439a8,0x361fbc00,0xbb6439a8,0x3b648000,0xb61fb9a8,0xb61f3c00,0x3b64b9a8,0xbb640000,0x361f39a8,
0xb8723c00,0x3bd9b61f,0xb23eb9a8,0xbaa73b64,0xbaa78000,0xb23e3b64,0x3bd9b9a8,0xb872b61f,0x3aa78000,0x323ebb64,0xbbd939a8,0x3872361f,0xb8723c00,0x3bd9b61f,0xb23eb9a8,0xbaa73b64,
0xbbd93c00,0xbaa73b64,0xb87239a8,0xb23e361f,0x323e8000,0x3872b61f,0x3aa7b9a8,0x3bd9bb64,0x323e8000,0x3872b61f,0x3aa7b9a8,0x3bd9bb64,0x3bd9bc00,0x3aa7bb64,0x3872b9a8,0x323eb61f,
0xbc003c00,0xbc003c00,0xbc003c00,0xbc003c00,0xbc003c00,0xbc003c00,0xbc003c00,0xbc003c00,0x80008000,0x80000000,0x80000000,0x80000000,0x80000000,0x80000000,0x0,0x80000000,
0xb8728000,0xbbd93b64,0xb23e39a8,0x3aa7b61f,0xbaa73c00,0x323e361f,0x3bd9b9a8,0x3872bb64,0xbaa73c00,0x323e361f,0x3bd9b9a8,0x3872bb64,0x38728000,0x3bd9bb64,0x323eb9a8,0xbaa7361f,
0x3b64bc00,0x361fb9a8,0xb61f8000,0xbb6439a8,0xbb643c00,0xb61f39a8,0x361f0000,0x3b64b9a8,0xb61f8000,0xbb6439a8,0xbb643c00,0xb61f39a8,0x361f8000,0x3b64b9a8,0x3b64bc00,0x361fb9a8,
0x3bd98000,0xbaa7361f,0x3872b9a8,0xb23e3b64,0xb23ebc00,0x38723b64,0xbaa7b9a8,0x3bd9361f,0x323e3c00,0xb872bb64,0x3aa739a8,0xbbd9b61f,0x3bd98000,0xbaa7361f,0x3872b9a8,0xb23e3b64,
0x3c008000,0xbc008000,0x3c000000,0xbc008000,0x3c000000,0xbc008000,0x3c000000,0xbc000000,0x80003c00,0xbc00,0x80003c00,0x8000bc00,0x80003c00,0xbc00,0x80003c00,0xbc00,
0x38723c00,0xbbd9b61f,0x323eb9a8,0x3aa73b64,0x3aa78000,0x323e3b64,0xbbd9b9a8,0x3872b61f,0xbaa78000,0xb23ebb64,0x3bd939a8,0xb872361f,0x38723c00,0xbbd9b61f,0x323eb9a8,0x3aa73b64,
0xbb640000,0x361fb9a8,0x361f3c00,0xbb64b9a8,0x3b648000,0xb61f39a8,0xb61fbc00,0x3b6439a8,0xb61fbc00,0x3b6439a8,0xbb640000,0x361fb9a8,0x361f3c00,0xbb64b9a8,0x3b648000,0xb61f39a8,
0x39a83c00,0xb9a80000,0xb9a8bc00,0x39a88000,0x39a83c00,0xb9a80000,0xb9a8bc00,0x39a88000,0xb9a88000,0xb9a8bc00,0x39a88000,0x39a83c00,0xb9a80000,0xb9a8bc00,0x39a88000,0x39a83c00,
0x38723c00,0xbbd9b61f,0x323eb9a8,0x3aa73b64,0xbaa70000,0xb23ebb64,0x3bd939a8,0xb872361f,0xbaa78000,0xb23ebb64,0x3bd939a8,0xb872361f,0xb872bc00,0x3bd9361f,0xb23e39a8,0xbaa7bb64,
0xb61fbc00,0x3b6439a8,0xbb640000,0x361fb9a8,0x361f3c00,0xbb64b9a8,0x3b648000,0xb61f39a8,0x3b648000,0xb61f39a8,0xb61fbc00,0x3b6439a8,0xbb648000,0x361fb9a8,0x361f3c00,0xbb64b9a8,
0x3bd98000,0xbaa7361f,0x3872b9a8,0xb23e3b64,0x323e3c00,0xb872bb64,0x3aa739a8,0xbbd9b61f,0x323e3c00,0xb872bb64,0x3aa739a8,0xbbd9b61f,0xbbd98000,0x3aa7b61f,0xb87239a8,0x323ebb64,
0xb9a88000,0xb9a83c00,0x39a88000,0x39a8bc00,0xb9a80000,0xb9a83c00,0x39a88000,0x39a8bc00,0xb9a83c00,0x39a88000,0x39a8bc00,0xb9a80000,0xb9a83c00,0x39a88000,0x39a8bc00,0xb9a88000,
0xb8728000,0xbbd93b64,0xb23e39a8,0x3aa7b61f,0x3aa7bc00,0xb23eb61f,0xbbd939a8,0xb8723b64,0xbaa73c00,0x323e361f,0x3bd9b9a8,0x3872bb64,0xb8728000,0xbbd93b64,0xb23e39a8,0x3aa7b61f,
0x361f8000,0x3b64b9a8,0x3b64bc00,0x361fb9a8,0xb61f8000,0xbb6439a8,0xbb643c00,0xb61f39a8,0x3b64bc00,0x361fb9a8,0xb61f8000,0xbb6439a8,0xbb643c00,0xb61f39a8,0x361f8000,0x3b64b9a8,
0xbbd93c00,0xbaa73b64,0xb87239a8,0xb23e361f,0xb23e8000,0xb872361f,0xbaa739a8,0xbbd93b64,0x323e8000,0x3872b61f,0x3aa7b9a8,0x3bd9bb64,0xbbd93c00,0xbaa73b64,0xb87239a8,0xb23e361f,
0xb8723c00,0x3bd9b61f,0xb23eb9a8,0xbaa73b64,0x3aa78000,0x323ebb64,0xbbd939a8,0x3872361f,0x3aa78000,0x323ebb64,0xbbd939a8,0x3872361f,0x3872bc00,0xbbd9361f,0x323e39a8,0x3aa7bb64,
0xb9a83c00,0x39a80000,0x39a8bc00,0xb9a88000,0xb9a83c00,0x39a88000,0x39a8bc00,0xb9a88000,0x39a88000,0x39a8bc00,0xb9a88000,0xb9a83c00,0x39a80000,0x39a8bc00,0xb9a88000,0xb9a83c00,
0xbbd98000,0x3aa7361f,0xb872b9a8,0x323e3b64,0xb23e3c00,0x3872bb64,0xbaa739a8,0x3bd9b61f,0xb23e3c00,0x3872bb64,0xbaa739a8,0x3bd9b61f,0x3bd98000,0xbaa7b61f,0x387239a8,0xb23ebb64,
0x361fbc00,0xbb6439a8,0x3b640000,0xb61fb9a8,0xb61f3c00,0x3b64b9a8,0xbb648000,0x361f39a8,0xbb648000,0x361f39a8,0x361fbc00,0xbb6439a8,0x3b648000,0xb61fb9a8,0xb61f3c00,0x3b64b9a8,
0x38728000,0x3bd93b64,0x323e39a8,0xbaa7b61f,0xbaa7bc00,0x323eb61f,0x3bd939a8,0x38723b64,0x3aa73c00,0xb23e361f,0xbbd9b9a8,0xb872bb64,0x38728000,0x3bd93b64,0x323e39a8,0xbaa7b61f,
0x39a88000,0x39a83c00,0xb9a88000,0xb9a8bc00,0x39a80000,0x39a83c00,0xb9a80000,0xb9a8bc00,0x39a83c00,0xb9a88000,0xb9a8bc00,0x39a88000,0x39a83c00,0xb9a88000,0xb9a8bc00,0x39a80000,
0x3bd93c00,0x3aa73b64,0x387239a8,0x323e361f,0x323e8000,0x3872361f,0x3aa739a8,0x3bd93b64,0xb23e8000,0xb872b61f,0xbaa7b9a8,0xbbd9bb64,0x3bd93c00,0x3aa73b64,0x387239a8,0x323e361f,
0xb61f8000,0xbb64b9a8,0xbb64bc00,0xb61fb9a8,0x361f8000,0x3b6439a8,0x3b643c00,0x361f39a8,0xbb64bc00,0xb61fb9a8,0x361f0000,0x3b6439a8,0x3b643c00,0x361f39a8,0xb61f8000,0xbb64b9a8,
0x0,0x0,0x0,0x0,0x0,0x0,0x0,0x0,0x3c003c00,0x3c003c00,0x3c003c00,0x3c003c00,0x3c003c00,0x3c003c00,0x3c003c00,0x3c003c00,
0x323e0000,0x3872361f,0x3aa739a8,0x3bd93b64,0x3bd93c00,0x3aa73b64,0x387239a8,0x323e361f,0x3bd93c00,0x3aa73b64,0x387239a8,0x323e361f,0xb23e0000,0xb872b61f,0xbaa7b9a8,0xbbd9bb64,
0xb61f0000,0xbb64b9a8,0xbb64bc00,0xb61fb9a8,0x361f0000,0x3b6439a8,0x3b643c00,0x361f39a8,0xbb64bc00,0xb61fb9a8,0x361f8000,0x3b6439a8,0x3b643c00,0x361f39a8,0xb61f0000,0xbb64b9a8,
0xbaa7bc00,0x323eb61f,0x3bd939a8,0x38723b64,0x38720000,0x3bd93b64,0x323e39a8,0xbaa7b61f,0x38728000,0x3bd93b64,0x323e39a8,0xbaa7b61f,0x3aa73c00,0xb23e361f,0xbbd9b9a8,0xb872bb64,
0x3c00,0x8000bc00,0x3c00,0x8000bc00,0x3c00,0x8000bc00,0x80003c00,0x8000bc00,0x3c000000,0xbc000000,0x3c008000,0xbc000000,0x3c008000,0xbc000000,0x3c008000,0xbc000000,
0xb23e3c00,0x3872bb64,0xbaa739a8,0x3bd9b61f,0xbbd90000,0x3aa7361f,0xb872b9a8,0x323e3b64,0x3bd90000,0xbaa7b61f,0x387239a8,0xb23ebb64,0xb23e3c00,0x3872bb64,0xbaa739a8,0x3bd9b61f,
0x361fbc00,0xbb6439a8,0x3b648000,0xb61fb9a8,0xb61f3c00,0x3b64b9a8,0xbb640000,0x361f39a8,0xbb640000,0x361f39a8,0x361fbc00,0xbb6439a8,0x3b640000,0xb61fb9a8,0xb61f3c00,0x3b64b9a8,
0x3aa78000,0x323ebb64,0xbbd939a8,0x3872361f,0xb8723c00,0x3bd9b61f,0xb23eb9a8,0xbaa73b64,0x3872bc00,0xbbd9361f,0x323e39a8,0x3aa7bb64,0x3aa70000,0x323ebb64,0xbbd939a8,0x3872361f,
0xb23e0000,0xb872361f,0xbaa739a8,0xbbd93b64,0xbbd93c00,0xbaa73b64,0xb87239a8,0xb23e361f,0xbbd93c00,0xbaa73b64,0xb87239a8,0xb23e361f,0x323e8000,0x3872b61f,0x3aa7b9a8,0x3bd9bb64,
0x0,0x8000,0x8000,0x8000,0x8000,0x8000,0x80008000,0x8000,0xbc003c00,0xbc003c00,0xbc003c00,0xbc003c00,0xbc003c00,0xbc003c00,0xbc003c00,0xbc003c00,
0x3aa7bc00,0xb23eb61f,0xbbd939a8,0xb8723b64,0xb8720000,0xbbd93b64,0xb23e39a8,0x3aa7b61f,0xb8728000,0xbbd93b64,0xb23e39a8,0x3aa7b61f,0xbaa73c00,0x323e361f,0x3bd9b9a8,0x3872bb64,
0x361f0000,0x3b64b9a8,0x3b64bc00,0x361fb9a8,0xb61f0000,0xbb6439a8,0xbb643c00,0xb61f39a8,0x3b64bc00,0x361fb9a8,0xb61f8000,0xbb6439a8,0xbb643c00,0xb61f39a8,0x361f0000,0x3b64b9a8,
0x323e3c00,0xb872bb64,0x3aa739a8,0xbbd9b61f,0x3bd98000,0xbaa7361f,0x3872b9a8,0xb23e3b64,0xbbd90000,0x3aa7b61f,0xb87239a8,0x323ebb64,0x323e3c00,0xb872bb64,0x3aa739a8,0xbbd9b61f,
0x80003c00,0xbc00,0x80003c00,0x8000bc00,0x80003c00,0xbc00,0x80003c00,0xbc00,0xbc000000,0x3c000000,0xbc008000,0x3c000000,0xbc008000,0x3c000000,0xbc008000,0x3c008000,
0xbaa78000,0xb23ebb64,0x3bd939a8,0xb872361f,0x38723c00,0xbbd9b61f,0x323eb9a8,0x3aa73b64,0xb872bc00,0x3bd9361f,0xb23e39a8,0xbaa7bb64,0xbaa70000,0xb23ebb64,0x3bd939a8,0xb872361f,
0xb61fbc00,0x3b6439a8,0xbb640000,0x361fb9a8,0x361f3c00,0xbb64b9a8,0x3b648000,0xb61f39a8,0x3b648000,0xb61f39a8,0xb61fbc00,0x3b6439a8,0xbb640000,0x361fb9a8,0x361f3c00,0xbb64b9a8,
0x39a80000,0x39a83c00,0xb9a80000,0xb9a8bc00,0x39a88000,0x39a83c00,0xb9a80000,0xb9a8bc00,0x39a83c00,0xb9a80000,0xb9a8bc00,0x39a88000,0x39a83c00,0xb9a80000,0xb9a8bc00,0x39a88000,
0x3aa70000,0x323e3b64,0xbbd9b9a8,0x3872b61f,0x38723c00,0xbbd9b61f,0x323eb9a8,0x3aa73b64,0x38723c00,0xbbd9b61f,0x323eb9a8,0x3aa73b64,0xbaa70000,0xb23ebb64,0x3bd939a8,0xb872361f,
0xbb640000,0x361fb9a8,0x361f3c00,0xbb64b9a8,0x3b640000,0xb61f39a8,0xb61fbc00,0x3b6439a8,0xb61fbc00,0x3b6439a8,0xbb640000,0x361fb9a8,0x361f3c00,0xbb64b9a8,0x3b648000,0xb61f39a8,
0xb23ebc00,0x38723b64,0xbaa7b9a8,0x3bd9361f,0x3bd90000,0xbaa7361f,0x3872b9a8,0xb23e3b64,0x3bd98000,0xbaa7361f,0x3872b9a8,0xb23e3b64,0x323e3c00,0xb872bb64,0x3aa739a8,0xbbd9b61f,
0xb9a83c00,0x39a88000,0x39a8bc00,0xb9a80000,0xb9a83c00,0x39a88000,0x39a8bc00,0xb9a88000,0x39a80000,0x39a8bc00,0xb9a80000,0xb9a83c00,0x39a88000,0x39a8bc00,0xb9a80000,0xb9a83c00,
0xbaa73c00,0x323e361f,0x3bd9b9a8,0x3872bb64,0xb8728000,0xbbd93b64,0xb23e39a8,0x3aa7b61f,0x38720000,0x3bd9bb64,0x323eb9a8,0xbaa7361f,0xbaa73c00,0x323e361f,0x3bd9b9a8,0x3872bb64,
0x3b64bc00,0x361fb9a8,0xb61f8000,0xbb6439a8,0xbb643c00,0xb61f39a8,0x361f8000,0x3b64b9a8,0xb61f0000,0xbb6439a8,0xbb643c00,0xb61f39a8,0x361f0000,0x3b64b9a8,0x3b64bc00,0x361fb9a8,
0x323e8000,0x3872b61f,0x3aa7b9a8,0x3bd9bb64,0xbbd93c00,0xbaa73b64,0xb87239a8,0xb23e361f,0x3bd9bc00,0x3aa7bb64,0x3872b9a8,0x323eb61f,0x323e0000,0x3872b61f,0x3aa7b9a8,0x3bd9bb64,
0xbaa70000,0xb23e3b64,0x3bd9b9a8,0xb872b61f,0xb8723c00,0x3bd9b61f,0xb23eb9a8,0xbaa73b64,0xb8723c00,0x3bd9b61f,0xb23eb9a8,0xbaa73b64,0x3aa78000,0x323ebb64,0xbbd939a8,0x3872361f,
0xb9a80000,0xb9a83c00,0x39a80000,0x39a8bc00,0xb9a88000,0xb9a83c00,0x39a80000,0x39a8bc00,0xb9a83c00,0x39a80000,0x39a8bc00,0xb9a88000,0xb9a83c00,0x39a88000,0x39a8bc00,0xb9a88000,
0x323ebc00,0xb8723b64,0x3aa7b9a8,0xbbd9361f,0xbbd90000,0x3aa7361f,0xb872b9a8,0x323e3b64,0xbbd98000,0x3aa7361f,0xb872b9a8,0x323e3b64,0xb23e3c00,0x3872bb64,0xbaa739a8,0x3bd9b61f,
0x3b640000,0xb61fb9a8,0xb61f3c00,0x3b64b9a8,0xbb640000,0x361f39a8,0x361fbc00,0xbb6439a8,0x361fbc00,0xbb6439a8,0x3b640000,0xb61fb9a8,0xb61f3c00,0x3b64b9a8,0xbb648000,0x361f39a8,
0x3aa73c00,0xb23e361f,0xbbd9b9a8,0xb872bb64,0x38728000,0x3bd93b64,0x323e39a8,0xbaa7b61f,0xb8720000,0xbbd9bb64,0xb23eb9a8,0x3aa7361f,0x3aa73c00,0xb23e361f,0xbbd9b9a8,0xb872bb64,
0x39a83c00,0xb9a88000,0xb9a8bc00,0x39a88000,0x39a83c00,0xb9a88000,0xb9a8bc00,0x39a80000,0xb9a80000,0xb9a8bc00,0x39a80000,0x39a83c00,0xb9a88000,0xb9a8bc00,0x39a88000,0x39a83c00,
0xb23e8000,0xb872b61f,0xbaa7b9a8,0xbbd9bb64,0x3bd93c00,0x3aa73b64,0x387239a8,0x323e361f,0xbbd9bc00,0xbaa7bb64,0xb872b9a8,0xb23eb61f,0xb23e0000,0xb872b61f,0xbaa7b9a8,0xbbd9bb64,
0xbb64bc00,0xb61fb9a8,0x361f0000,0x3b6439a8,0x3b643c00,0x361f39a8,0xb61f8000,0xbb64b9a8,0x361f0000,0x3b6439a8,0x3b643c00,0x361f39a8,0xb61f0000,0xbb64b9a8,0xbb64bc00,0xb61fb9a8,
};
__device__ __align__(1024) bf16 g_x1T[DM * XP];
__device__ __align__(1024) bf16 g_x2T[DM * XP];
constexpr int FP = SEQ + 32;
__device__ __align__(1024) uint32_t g_fin[DM / 2][FP];
__device__ __align__(1024) float g_sums[2][2][SEQ];

#define TS_DECL
#define TS_ARG
#define TS_PASS
#define TS_PHASE(p)
#define TS(i)
#define TSX(row, i)
#define TS_BEGIN
#define TS_END

__device__ __align__(1024) uint32_t g_keo[DM / 2][2048];
__device__ __align__(128) uint32_t g_ksc[DM];

struct cplx { float r, i; };
__device__ __forceinline__ cplx cmul(cplx a, cplx b) {
    cplx o;
    o.r = fmaf(a.r, b.r, -a.i * b.i);
    o.i = fmaf(a.r, b.i, a.i * b.r);
    return o;
}
__device__ __forceinline__ cplx csq(cplx a) {
    cplx o;
    o.r = fmaf(a.r, a.r, -a.i * a.i);
    o.i = 2.f * a.r * a.i;
    return o;
}
__device__ __forceinline__ cplx cexp_p(float arl, float ai, float p) {
    float mag = ex2(arl * p);
    float ang = ai * p;
    float n = rintf(ang * 0.15915494309189535f);
    float r = fmaf(n, -6.2831854820251465f, ang);
    r = fmaf(n, 1.7484555e-7f, r);
    cplx o;
    o.r = mag * __cosf(r);
    o.i = mag * __sinf(r);
    return o;
}

__device__ __forceinline__ uint32_t pack2h(float lo, float hi) {
    uint32_t r;
    asm("cvt.rn.f16x2.f32 %0, %1, %2;" : "=r"(r) : "f"(hi), "f"(lo));
    return r;
}
__device__ __forceinline__ uint32_t hmul(uint32_t a, uint32_t b) { uint32_t d; asm("mul.rn.f16x2 %0, %1, %2;" : "=r"(d) : "r"(a), "r"(b)); return d; }
__device__ __forceinline__ uint32_t hfma(uint32_t a, uint32_t b, uint32_t c) { uint32_t d; asm("fma.rn.f16x2 %0, %1, %2, %3;" : "=r"(d) : "r"(a), "r"(b), "r"(c)); return d; }
__device__ __forceinline__ uint32_t hfms(uint32_t a, uint32_t b, uint32_t c) {
    uint32_t d;
    asm("{\n.reg .b32 n;\nneg.f16x2 n, %1;\nfma.rn.f16x2 %0, n, %2, %3;\n}" : "=r"(d) : "r"(a), "r"(b), "r"(c));
    return d;
}
__device__ __forceinline__ uint32_t hadd(uint32_t a, uint32_t b) { uint32_t d; asm("add.rn.f16x2 %0, %1, %2;" : "=r"(d) : "r"(a), "r"(b)); return d; }
__device__ __forceinline__ uint32_t hsub(uint32_t a, uint32_t b) { uint32_t d; asm("sub.rn.f16x2 %0, %1, %2;" : "=r"(d) : "r"(a), "r"(b)); return d; }
__device__ __forceinline__ uint4 ldg_tab(int tab, int t) {
    uint4 v;
    asm volatile("ld.global.nc.v4.u32 {%0,%1,%2,%3}, [%4];" : "=r"(v.x), "=r"(v.y), "=r"(v.z), "=r"(v.w) : "l"((const uint4*)c_fft + tab * 128 + t));
    return v;
}
__device__ __forceinline__ uint32_t u4(const uint4& v, int i) { return i == 0 ? v.x : i == 1 ? v.y : i == 2 ? v.z : v.w; }
struct cpair { uint32_t r, i; };
__device__ __forceinline__ cpair pmul(cpair p, uint32_t z) {
    const __half2 zv = *reinterpret_cast<const __half2*>(&z), pr = *reinterpret_cast<const __half2*>(&p.r), pi = *reinterpret_cast<const __half2*>(&p.i);
    const __half2 zr = __low2half2(zv), zi = __high2half2(zv);
    const __half2 a = __hfma2(__hneg2(pi), zi, __hmul2(pr, zr)), b = __hfma2(pi, zr, __hmul2(pr, zi));
    return {*reinterpret_cast<const uint32_t*>(&a), *reinterpret_cast<const uint32_t*>(&b)};
}
__device__ __forceinline__ uint32_t packz(cplx z) { return pack2h(z.r, z.i); }
__device__ __forceinline__ void wgmma_kg(float (&d)[24], uint64_t da, uint64_t db, int scale_d) {
    asm volatile("{\n.reg .pred p;\nsetp.ne.b32 p, %26, 0;\n"
                 "wgmma.mma_async.sync.aligned.m64n48k16.f32.f16.f16 "
                 "{%0,%1,%2,%3,%4,%5,%6,%7,%8,%9,%10,%11,%12,%13,%14,%15,%16,%17,%18,%19,%20,%21,%22,%23}, %24, %25, p, 1, 1, 1, 1;\n}\n"
                 : "+f"(d[0]), "+f"(d[1]), "+f"(d[2]), "+f"(d[3]), "+f"(d[4]), "+f"(d[5]), "+f"(d[6]), "+f"(d[7]), "+f"(d[8]), "+f"(d[9]),
                   "+f"(d[10]), "+f"(d[11]), "+f"(d[12]), "+f"(d[13]), "+f"(d[14]), "+f"(d[15]), "+f"(d[16]), "+f"(d[17]), "+f"(d[18]), "+f"(d[19]),
                   "+f"(d[20]), "+f"(d[21]), "+f"(d[22]), "+f"(d[23])
                 : "l"(da), "l"(db), "r"(scale_d));
}

struct SsmParams { const bf16 *lar, *aim, *cre, *cim, *logdt, *dskip; };
constexpr int KG_TABLES = 6 * 16384, KG_RES = 3136, KG_IDX = 6 * KG_RES, KG_DUMP = KG_IDX + 4096;
struct KgShared { uint32_t kmax[6]; };
struct KgParams { uint32_t l[3], a[3], r[3], i[3], dt, ds; };

__device__ __forceinline__ void kgen_load(KgParams& kp, int d0, int warp, int lane, const SsmParams& sp) {
    const int d = d0 + (warp < 8 ? 2 * (warp >> 2) + (warp & 1) : 4), idx = d * (NMODE / 2) + lane;
    const bf16 *pr = (warp & 2) ? sp.cre : sp.lar, *pi = (warp & 2) ? sp.cim : sp.aim;
#pragma unroll
    for (int j = 0; j < 3; j++) {
        kp.l[j] = __ldg((const uint32_t*)sp.lar + idx + 32 * j); kp.a[j] = __ldg((const uint32_t*)sp.aim + idx + 32 * j);
        kp.r[j] = __ldg((const uint32_t*)pr + idx + 32 * j); kp.i[j] = __ldg((const uint32_t*)pi + idx + 32 * j);
    }
    kp.dt = __ldg((const uint16_t*)sp.logdt + d);
    kp.ds = __ldg((const uint16_t*)sp.dskip + d0 + min(warp >> 1, 4));
}

struct KgAnchors { uint32_t v[8]; };
__device__ __forceinline__ KgAnchors kg_anchor_lo(const KgParams& kp, uint32_t sel, float dt) {
    auto B = [&](uint32_t v) { return __uint_as_float(__byte_perm(v, 0u, sel)); };
    const float arl = -rbf(ex2(B(kp.l[0]) * 1.4426950408889634f)) * dt * 1.4426950408889634f, ai = B(kp.a[0]) * dt;
    const cplx z8 = cexp_p(arl, ai, 8.f), z16 = csq(z8), z24 = cmul(z16, z8), z32 = csq(z16), z64 = csq(z32), z128 = csq(z64), z192 = cmul(z128, z64);
    return {{pack2h(1.f, z8.r), pack2h(0.f, z8.i), pack2h(z16.r, z24.r), pack2h(z16.i, z24.i), packz(z32), packz(z64), packz(z128), packz(z192)}};
}
__device__ __forceinline__ KgAnchors kg_anchor_hi(const KgParams& kp, uint32_t sel, float dt, float cs) {
    auto B = [&](uint32_t v) { return __uint_as_float(__byte_perm(v, 0u, sel)); };
    const float arl = -rbf(ex2(B(kp.l[0]) * 1.4426950408889634f)) * dt * 1.4426950408889634f, ai = B(kp.a[0]) * dt;
    const cplx z1 = cexp_p(arl, -ai, 1.f), z2 = csq(z1), z4 = csq(z2), z256 = cexp_p(arl, -ai, 256.f), z512 = csq(z256), z1024 = csq(z512);
    const cplx H0 = {B(kp.r[0]) * cs, -B(kp.i[0]) * cs}, H4 = cmul(H0, z4);
    return {{pack2h(H0.r, H4.r), pack2h(H0.i, H4.i), packz(z1), packz(z2), packz(z256), packz(z512), packz(z1024), 0u}};
}

template <class Hook>
__device__ __forceinline__ void kgen_tables(KgParams& kp, uint32_t scr, uint32_t dump, KgShared* ks, int warp, int lane, Hook hook TS_ARG) {
    const int wg = warp >> 2, half = warp & 1, sw = lane & 7;
    const bool hi = warp & 2;
    TS(23);
    const float dt = rbf(ex2(bf_lo(kp.dt) * 1.4426950408889634f));
    uint32_t sel = (wg == 2 && half) ? 0x3244u : 0x1044u;
    float cs = 0.f;
    KgAnchors an;
    if (hi) {
        uint32_t m = 0;
#pragma unroll
        for (int j = 0; j < 3; j++) m = __vmaxu2(m, __vmaxu2(kp.r[j] & 0x7FFF7FFFu, kp.i[j] & 0x7FFF7FFFu));
        m = __reduce_max_sync(~0u, max(m << 16, m & 0xFFFF0000u));
        const uint32_t e = min(max(__float_as_uint(2.f * dt * __uint_as_float(m)) >> 23, 2u), 252u);
        cs = 2.f * dt * __uint_as_float((253u - e) << 23);
        if (lane == 0) sts32(dump + (2 * wg + half) * KG_RES, (e + 1u) << 23);
        an = kg_anchor_hi(kp, sel, dt, cs);
    } else {
        an = kg_anchor_lo(kp, sel, dt);
    }
    if (an.v[0] != 0xFFFFFFFFu) hook();
    float acc[24];
    const int nstep = wg == 2 ? 3 : 6;
#pragma unroll 1
    for (int c = 0; c < nstep; c++) {
        if (wg < 2) sel ^= 0x2200u;
        if (wg == 2 || (c & 1)) {
#pragma unroll
            for (int j = 0; j < 2; j++) { kp.l[j] = kp.l[j + 1]; kp.a[j] = kp.a[j + 1]; kp.r[j] = kp.r[j + 1]; kp.i[j] = kp.i[j + 1]; }
        }
        const uint32_t buf = scr + (2 * wg + (c & 1)) * 16384, tb = buf + lane * 128;
        if (!hi) {
            cpair p[4];
            p[0] = {an.v[0], an.v[1]}; p[1] = {an.v[2], an.v[3]};
            p[2] = pmul(p[0], an.v[4]); p[3] = pmul(p[1], an.v[4]);
#pragma unroll
            for (int j = 0; j < 4; j++) {
                cpair v[4];
#pragma unroll
                for (int i = 0; i < 4; i++) v[i] = j ? pmul(p[i], an.v[4 + j]) : p[i];
                const uint32_t a = tb + (((4 * half + j) ^ sw) << 4);
                sts128(a, make_uint4(v[0].r, v[1].r, v[2].r, v[3].r));
                sts128(a + 4096, make_uint4(v[0].i, v[1].i, v[2].i, v[3].i));
            }
            an = kg_anchor_lo(kp, sel, dt);
        } else {
            const uint32_t h1 = an.v[2], h2 = an.v[3], h256 = an.v[4], h512 = an.v[5], h1024 = an.v[6];
            cpair p[11];
            p[0] = {an.v[0], an.v[1]};
            p[1] = pmul(p[0], h2); p[2] = pmul(p[0], h1); p[3] = pmul(p[1], h1);
            p[4] = pmul(p[0], h256); p[5] = pmul(p[1], h256); p[6] = pmul(p[0], h512); p[7] = pmul(p[4], h512);
            p[8] = pmul({__byte_perm(p[0].r, p[4].r, 0x5410), __byte_perm(p[0].i, p[4].i, 0x5410)}, h1024);
            p[9] = pmul(p[8], h512); p[10] = pmul(p[8], h1024);
#pragma unroll
            for (int j = 0; j < 3; j++) {
                const uint32_t a = tb + 8192 + (((3 * half + j) ^ sw) << 4);
                sts128(a, make_uint4(p[4 * j].r, p[4 * j + 1].r, p[4 * j + 2].r, p[j < 2 ? 4 * j + 3 : 10].r));
                sts128(a + 4096, make_uint4(p[4 * j].i, p[4 * j + 1].i, p[4 * j + 2].i, p[j < 2 ? 4 * j + 3 : 10].i));
            }
            an = kg_anchor_hi(kp, sel, dt, cs);
        }
        if (c == 0) TS(24);
        if (c == 2) TS(26);
        fence_async_smem();
        wg_wait<0>();
        named_bar(5 + wg, 128);
        if (c == 1) TS(25);
        if (c == 2) TS(28);
        const uint64_t da = mkdesc(buf, 4096, 1024, 1);
        wg_fence();
#pragma unroll
        for (int k = 0; k < 4; k++) wgmma_kg(acc, da + k * 128, da + 512 + k * 128, k > 0 || c > 0);
        wg_commit();
    }
    const int lo0 = 16 * half + (lane >> 2);
    const uint32_t ob = dump + (2 * wg + (hi ? 1 : 0)) * KG_RES, o = ob + (lo0 * 24 + 2 * (lo0 >> 2) + 2 * (lane & 3)) * 4;
    const float ci = __uint_as_float(lds32(ob));
    const float ds = (lane == 0 && warp <= 8 && !half) ? bf_lo(kp.ds) : 0.f;
    named_bar(5 + wg, 128);
    wg_wait<0>();
    float m = 0.f;
#pragma unroll
    for (int j = 0; j < 3; j++)
#pragma unroll
        for (int h = 0; h < 2; h++) {
            const float v0 = fmaf(ci, hi ? acc[12 + 4 * j + 2 * h] : acc[4 * j + 2 * h], j + h ? 0.f : ds), v1 = ci * (hi ? acc[13 + 4 * j + 2 * h] : acc[4 * j + 2 * h + 1]);
            asm volatile("st.shared.v2.f32 [%0], {%1, %2};" ::"r"(o + h * 784 + j * 32), "f"(v0), "f"(v1) : "memory");
            m = fmaxf(m, fmaxf(fabsf(v0), fabsf(v1)));
        }
    const uint32_t mm = __reduce_max_sync(~0u, __float_as_uint(m));
    if (lane == 0) asm volatile("red.shared.max.u32 [%0], %1;" ::"r"(s2u(&ks->kmax[2 * wg + (hi ? 1 : 0)])), "r"(mm) : "memory");
}

__device__ __forceinline__ void kgen_expand(int d0, uint32_t dump, KgShared* ks, int ht TS_ARG) {
    const int lane = ht & 31;
    auto F = [](uint32_t x) { return __uint_as_float(x); };
#pragma unroll 1
    for (int task = ht >> 5; task < 20; task += 3) {
        const int c = task >> 2, it = (task & 3) * 32 + lane, a = it >> 2, d = d0 + c;
        const uint4 o0 = lds128(dump + KG_IDX + it * 16), o1 = lds128(dump + KG_IDX + 2048 + it * 16);
        const uint32_t e = min(max(__float_as_uint(F(ks->kmax[c]) + (c == 4 ? F(ks->kmax[5]) : 0.f)) >> 23, 4u), 250u), b = dump + c * KG_RES;
        const float sc = __uint_as_float((253u - e) << 23);
        if (it == 0) g_ksc[d] = e;
        float x[16];
#pragma unroll
        for (int i = 0; i < 8; i++) {
            const uint32_t w = u4(i < 4 ? o0 : o1, i & 3);
            x[2 * i] = F(lds32(b + (w & 0xFFFF))); x[2 * i + 1] = F(lds32(b + (w >> 16)));
        }
        if (c == 4) {
#pragma unroll
            for (int i = 0; i < 8; i++) {
                const uint32_t w = u4(i < 4 ? o0 : o1, i & 3);
                x[2 * i] += F(lds32(b + KG_RES + (w & 0xFFFF))); x[2 * i + 1] += F(lds32(b + KG_RES + (w >> 16)));
            }
        }
        uint32_t ev[4], ov[4];
#pragma unroll
        for (int i = 0; i < 4; i++) {
            ev[i] = pack2h((x[2 * i] + x[8 + 2 * i]) * sc, (x[2 * i + 1] + x[9 + 2 * i]) * sc);
            ov[i] = pack2h((x[2 * i] - x[8 + 2 * i]) * sc, (x[2 * i + 1] - x[9 + 2 * i]) * sc);
        }
        uint32_t* dst = &g_keo[d >> 1][a * 32 + (((4 * (d & 1) + (it & 3)) ^ (a & 7)) << 2)];
        stg128(dst, make_uint4(ev[0], ev[1], ev[2], ev[3]));
        stg128(dst + 1024, make_uint4(ov[0], ov[1], ov[2], ov[3]));
    }
}
__device__ __forceinline__ void wgmma_h64_rs(uint32_t (&d)[16], const uint4& a, uint64_t db, int scale_d) {
    asm volatile("{\n.reg .pred p;\nsetp.ne.b32 p, %21, 0;\n"
                 "wgmma.mma_async.sync.aligned.m64n64k16.f16.f16.f16 {%0,%1,%2,%3,%4,%5,%6,%7,%8,%9,%10,%11,%12,%13,%14,%15}, {%16,%17,%18,%19}, %20, p, 1, 1, 1;\n}\n"
                 : "+r"(d[0]), "+r"(d[1]), "+r"(d[2]), "+r"(d[3]), "+r"(d[4]), "+r"(d[5]), "+r"(d[6]), "+r"(d[7]), "+r"(d[8]), "+r"(d[9]),
                   "+r"(d[10]), "+r"(d[11]), "+r"(d[12]), "+r"(d[13]), "+r"(d[14]), "+r"(d[15])
                 : "r"(a.x), "r"(a.y), "r"(a.z), "r"(a.w), "l"(db), "r"(scale_d));
}
__device__ __forceinline__ void wgmma_h32_rs(uint32_t (&d)[8], const uint32_t (&a)[4], uint64_t db, int scale_d) {
    asm volatile("{\n.reg .pred p;\nsetp.ne.b32 p, %13, 0;\n"
                 "wgmma.mma_async.sync.aligned.m64n32k16.f16.f16.f16 {%0,%1,%2,%3,%4,%5,%6,%7}, {%8,%9,%10,%11}, %12, p, 1, 1, 0;\n}\n"
                 : "+r"(d[0]), "+r"(d[1]), "+r"(d[2]), "+r"(d[3]), "+r"(d[4]), "+r"(d[5]), "+r"(d[6]), "+r"(d[7])
                 : "r"(a[0]), "r"(a[1]), "r"(a[2]), "r"(a[3]), "l"(db), "r"(scale_d));
}
__device__ __forceinline__ void wgmma_sp64_rs(float (&d)[32], const uint4& a, uint64_t db, uint32_t meta, int scale_d) {
    asm volatile("{\n.reg .pred p;\nsetp.ne.b32 p, %38, 0;\n"
                 "wgmma.mma_async.sp.sync.aligned.m64n64k32.f32.f16.f16 "
                 "{%0,%1,%2,%3,%4,%5,%6,%7,%8,%9,%10,%11,%12,%13,%14,%15,%16,%17,%18,%19,%20,%21,%22,%23,%24,%25,%26,%27,%28,%29,%30,%31}, "
                 "{%32,%33,%34,%35}, %36, %37, 0, p, 1, 1, 1;\n}\n"
                 : "+f"(d[0]), "+f"(d[1]), "+f"(d[2]), "+f"(d[3]), "+f"(d[4]), "+f"(d[5]), "+f"(d[6]), "+f"(d[7]), "+f"(d[8]), "+f"(d[9]),
                   "+f"(d[10]), "+f"(d[11]), "+f"(d[12]), "+f"(d[13]), "+f"(d[14]), "+f"(d[15]), "+f"(d[16]), "+f"(d[17]), "+f"(d[18]), "+f"(d[19]),
                   "+f"(d[20]), "+f"(d[21]), "+f"(d[22]), "+f"(d[23]), "+f"(d[24]), "+f"(d[25]), "+f"(d[26]), "+f"(d[27]), "+f"(d[28]), "+f"(d[29]),
                   "+f"(d[30]), "+f"(d[31])
                 : "r"(a.x), "r"(a.y), "r"(a.z), "r"(a.w), "l"(db), "r"(meta), "r"(scale_d));
}

__device__ __forceinline__ void fft_stage(const uint32_t (&u)[2][2][4], uint32_t eo, int warp4, int lane) {
    const int mi = lane >> 3, mj = lane & 7;
#pragma unroll
    for (int c = 0; c < 2; c++) {
        const uint32_t a = eo + (8 * warp4 + mj) * 128 + (((4 * c + mi) ^ mj) << 4);
        stsm_x4(a, hadd(u[c][0][0], u[c][1][0]), hadd(u[c][0][1], u[c][1][1]), hadd(u[c][0][2], u[c][1][2]), hadd(u[c][0][3], u[c][1][3]));
        stsm_x4(a + 4096, hsub(u[c][0][0], u[c][1][0]), hsub(u[c][0][1], u[c][1][1]), hsub(u[c][0][2], u[c][1][2]), hsub(u[c][0][3], u[c][1][3]));
    }
    fence_async_smem();
}
template <class Mid>
__device__ __forceinline__ void fft_forward(const uint4 (&a1)[4], const uint4 (&tw)[4], uint32_t eo, uint32_t s2, uint32_t (&X)[2][2][8], Mid mid) {
    uint32_t dr[16], di[16];
    const uint64_t de = mkdesc(eo, 4096, 1024, 1), d2 = mkdesc(s2, 16, 1024, 1);
    wg_fence();
    wgmma_h64_rs(dr, a1[0], de, 0);
    wgmma_h64_rs(di, a1[2], de + 256, 0);
    wgmma_h64_rs(dr, a1[1], de + 128, 1);
    wgmma_h64_rs(di, a1[3], de + 384, 1);
    wg_commit();
    mid();
    wg_wait<0>();
#pragma unroll
    for (int c = 0; c < 2; c++) {
        uint32_t zr[2][4], zi[2][4];
#pragma unroll
        for (int p = 0; p < 2; p++)
#pragma unroll
            for (int i = 0; i < 4; i++) {
                const uint32_t r = dr[8 * c + 4 * p + i], m = di[8 * c + 4 * p + i], tr = u4(tw[p], i), ti = u4(tw[2 + p], i);
                zr[p][i] = hfms(m, ti, hmul(r, tr));
                zi[p][i] = hfma(m, tr, hmul(r, ti));
            }
        wg_fence();
        wgmma_h32_rs(X[c][0], zr[0], d2, 0);
        wgmma_h32_rs(X[c][1], zr[1], d2 + 4, 0);
        wgmma_h32_rs(X[c][0], zi[0], d2 + 2, 1);
        wgmma_h32_rs(X[c][1], zi[1], d2 + 6, 1);
        wg_commit();
    }
}

template <class Mid, class Ready>
__device__ __forceinline__ void conv_pair(int ch0, int layer, uint32_t eo, uint32_t zb, uint32_t s23, uint32_t kbar, int warp, int lane,
                                          uint4 (&a1)[4], uint4 (&tw)[4], Mid mid, Ready ready TS_ARG) {
    const int wg = warp >> 2, w = warp & 3, t = 32 * w + lane, g = lane >> 2, q = lane & 3, mi = lane >> 3, mj = lane & 7;
    const bf16* xT = g_x1T;
    const float* sums = g_sums[layer][0];
    uint32_t u[2][2][4], KH[2][2][8];
    TS(1);
    mbar_wait(kbar, 0);
    TS(2);
    fft_forward(a1, tw, eo, s23, KH, mid);
    const uint2 ke = ldg64(g_ksc + ch0);
    named_bar(1 + wg, 128);
#pragma unroll
    for (int i = 0; i < 4; i++) tw[i] = ldg_tab(4 + i, t);
    const uint32_t oscale[2] = {(ke.x + 3u) * 0x00800080u, (ke.y + 3u) * 0x00800080u};
    wg_wait<0>();
    TS(4);
    ready();
    TS(5);
    uint2 x[2][2][2];
    const int ra[2] = {16 * (8 * w + g) + 4 * q, 16 * (63 - 8 * w - g) + 4 * q};
    {
        uint4 s[2][2][2];
#pragma unroll
        for (int h = 0; h < 2; h++)
#pragma unroll
            for (int p = 0; p < 2; p++) {
                s[h][p][0] = ldg128(sums + 1024 * p + ra[h]);
                s[h][p][1] = ldg128(sums + SEQ + 1024 * p + ra[h]);
#pragma unroll
                for (int c = 0; c < 2; c++) x[c][h][p] = ldg64(xT + (size_t)(ch0 + c) * XP + 1024 * p + ra[h]);
            }
        TS(6);
#pragma unroll
        for (int h = 0; h < 2; h++)
#pragma unroll
            for (int j = 0; j < 4; j++) {
                const uint4 sa = s[h][j >> 1][0], sq = s[h][j >> 1][1];
                const float4 v = make_float4(__uint_as_float(u4(sa, 2 * (j & 1))), __uint_as_float(u4(sq, 2 * (j & 1))),
                                             __uint_as_float(u4(sa, 2 * (j & 1) + 1)), __uint_as_float(u4(sq, 2 * (j & 1) + 1)));
                const float m0 = v.x * (1.0f / DM), m1 = v.z * (1.0f / DM);
                const float r0 = frsq(fmaxf(fmaf(v.y, 1.0f / DM, fmaf(-m0, m0, 1e-5f)), 1e-5f));
                const float r1 = frsq(fmaxf(fmaf(v.w, 1.0f / DM, fmaf(-m1, m1, 1e-5f)), 1e-5f));
                const float c0 = -m0 * r0, c1 = -m1 * r1;
#pragma unroll
                for (int c = 0; c < 2; c++) {
                    const uint32_t xv = (j & 1) ? x[c][h][j >> 1].y : x[c][h][j >> 1].x;
                    u[c][h][j] = pack2h(fmaf(bf_lo(xv), r0, c0), fmaf(bf_hi(xv), r1, c1));
                }
            }
    }
    TS(8);
    uint32_t X[2][2][8], Y[2][2][8];
    fft_stage(u, eo, w, lane);
    TS(9);
    named_bar(1 + wg, 128);
    fft_forward(a1, tw, eo, s23, X, [] {});
    TS(10);
#pragma unroll
    for (int i = 0; i < 4; i++) a1[i] = ldg_tab(12 + i, t);
    const uint64_t d3 = mkdesc(s23 + 4096, 16, 1024, 1);
#pragma unroll
    for (int c = 0; c < 2; c++) {
        wg_wait<1>();
        TS(11 + c);
        uint32_t pr[2][4], pi[2][4];
#pragma unroll
        for (int i = 0; i < 4; i++) {
            const uint32_t er = X[c][0][i], ei = X[c][0][4 + i], orr = X[c][1][i], oi = X[c][1][4 + i];
            const uint32_t ar = KH[c][0][i], ai = KH[c][0][4 + i], br = KH[c][1][i], bi = KH[c][1][4 + i];
            pr[0][i] = hfms(bi, oi, hfma(br, orr, hfms(ai, ei, hmul(ar, er))));
            pi[0][i] = hfma(bi, orr, hfma(br, oi, hfma(ai, er, hmul(ar, ei))));
            pr[1][i] = hfms(ai, oi, hfma(ar, orr, hfms(bi, ei, hmul(br, er))));
            pi[1][i] = hfma(ai, orr, hfma(ar, oi, hfma(bi, er, hmul(br, ei))));
        }
        wg_fence();
        wgmma_h32_rs(Y[c][0], pr[0], d3, 0);
        wgmma_h32_rs(Y[c][1], pr[1], d3 + 4, 0);
        wgmma_h32_rs(Y[c][0], pi[0], d3 + 2, 1);
        wgmma_h32_rs(Y[c][1], pi[1], d3 + 6, 1);
        wg_commit();
    }
#pragma unroll
    for (int c = 0; c < 2; c++) {
        if (c == 0) wg_wait<1>(); else wg_wait<0>();
        TS(13 + c);
        uint32_t zr[2][4], zi[2][4];
#pragma unroll
        for (int p = 0; p < 2; p++)
#pragma unroll
            for (int i = 0; i < 4; i++) {
                const uint32_t r = Y[c][p][i], m = Y[c][p][4 + i], tr = u4(tw[p], i), ti = u4(tw[2 + p], i);
                zr[i & 1][2 * p + (i >> 1)] = hfma(m, ti, hmul(r, tr));
                zi[i & 1][2 * p + (i >> 1)] = hfms(r, ti, hmul(m, tr));
            }
        const int kr = 4 * (mj >> 1) + (mj & 1) + 2 * (mj >> 2), ki = kr ^ 2;
#pragma unroll
        for (int h = 0; h < 2; h++) {
            const uint32_t a = zb + (2 * w + h) * 2048;
            stsm_x4(a + kr * 128 + (((4 * c + mi) ^ (kr & 7)) << 4), zr[h][0], zr[h][1], zr[h][2], zr[h][3]);
            stsm_x4(a + ki * 128 + (((4 * c + mi) ^ (ki & 7)) << 4), zi[h][0], zi[h][1], zi[h][2], zi[h][3]);
        }
    }
    TS(15);
    fence_async_smem();
    TS(16);
    named_bar(1 + wg, 128);
    TS(17);
    float acc[32];
    const uint64_t dz = mkdesc(zb, 4096, 1024, 1);
    wg_fence();
#pragma unroll
    for (int ks = 0; ks < 4; ks++) wgmma_sp64_rs(acc, a1[ks], dz + ks * 256, 0x44EEEE44u, ks > 0);
    wg_commit();
    wg_wait<0>();
    TS(18);
#pragma unroll
    for (int p = 0; p < 2; p++) {
        uint32_t r[2][2][2];
#pragma unroll
        for (int c = 0; c < 2; c++)
#pragma unroll
            for (int j = 0; j < 2; j++) {
                const float* d = acc + 4 * (4 * c + 2 * p + j);
                const uint32_t y0 = pack2(d[0] + d[2], d[1] + d[3]), y1 = pack2(d[0] - d[2], d[1] - d[3]);
                asm("fma.rn.bf16x2 %0, %1, %2, %3;" : "=r"(r[c][0][j]) : "r"(y0), "r"(oscale[c]), "r"(j ? x[c][0][p].y : x[c][0][p].x));
                asm("fma.rn.bf16x2 %0, %1, %2, %3;" : "=r"(r[c][1][j]) : "r"(y1), "r"(oscale[c]), "r"(j ? x[c][1][p].y : x[c][1][p].x));
            }
#pragma unroll
        for (int h = 0; h < 2; h++) {
            if (layer == 0) {
#pragma unroll
                for (int c = 0; c < 2; c++) *(uint2*)(g_x2T + (size_t)(ch0 + c) * XP + 1024 * p + ra[h]) = make_uint2(r[c][h][0], r[c][h][1]);
            } else {
                const uint32_t v0 = __byte_perm(r[0][h][0], r[1][h][0], 0x5410);
                st_ll4((uint4*)&g_fin[ch0 >> 1][1024 * p + ra[h]], v0 ? v0 : 0x80000000u, __byte_perm(r[0][h][0], r[1][h][0], 0x7632),
                       __byte_perm(r[0][h][1], r[1][h][1], 0x5410), __byte_perm(r[0][h][1], r[1][h][1], 0x7632));
            }
        }
    }
    TS(19);
}

#define Q_SCHED 0
#define Q_WAITFOR(it) (Q_SCHED == 0 ? (it) - 2 : Q_SCHED == 1 ? ((it) == 3 ? 1 : 0) : Q_SCHED == 2 ? -1 : (it) - 1)
#define Q_S0 8
#define Q_WGATE 0
#define Q_ROT 0
#define O_ROT 0
#define K_EARLY 0
#define O_KAT 3
#define O_MASK 127u
#define O_DEPTH 3
#define O_GATE 0
#define A_HPOS 1
#define FIN_SLEEP 100
#define F_WDELAY 1200
constexpr int Q_ST = 4;
constexpr int Q_AB = 16384, Q_BB = 30720, Q_SB = Q_AB + Q_BB;
constexpr int Q_EROW = 336;
constexpr int Q_ESLOT = 8 * Q_EROW;
constexpr int Q_EOFF = Q_ST * Q_SB;
constexpr int Q_KG = 2 * Q_SB;
constexpr int Q_KDUMP = Q_EOFF + 16384;
static_assert(6 * Q_ESLOT <= 16384, "exchange slots");
static_assert(Q_KG + KG_TABLES <= Q_KDUMP, "kernel generation layout");
constexpr int Q_SMEM = Q_KDUMP + KG_DUMP;
constexpr int F_EO = Q_EOFF, F_S23 = F_EO + 3 * 8192;
static_assert(F_S23 + 8192 <= Q_SMEM, "convolution layout");
__host__ __device__ constexpr int w_grp(int j) { return j < 7 ? 2 * Q_SB + j * 12800 : 20480; }
constexpr int W_RES = 0, W_OUT = Q_SB;

constexpr int Q_ZERO = Q_EOFF + 4096, Q_WOT = Q_EOFF + 8320;

__device__ unsigned g_epoch;
__device__ __align__(1024) unsigned g_bar[4][16][32];
__device__ __align__(1024) uint4 g_wop[8][80][10][8];
__device__ __align__(1024) uint4 g_csp[8][16][96];
__device__ __align__(1024) uint4 g_stp[16][8][64];
__device__ __align__(1024) uint4 g_halo[128][2][5][32];
__device__ __align__(1024) uint4 g_of[8][16][8][5][32];

struct Bars { uint64_t full[Q_ST], empty[Q_ST], wfull[3], ex[7], res, go, qdone, att, prep, kf, ardy, hdone, fdone, idx, kdone, att1; };
constexpr int NBAR = sizeof(Bars) / 8;
__device__ __forceinline__ void grid_wait(const unsigned* c, int n, unsigned target, int lane) {
    const unsigned* p = c + 32 * min(lane, n - 1);
    unsigned v;
    int spin = 0;
    do { asm volatile("ld.relaxed.gpu.global.u32 %0, [%1];" : "=r"(v) : "l"(p) : "memory"); } while (!__all_sync(~0u, (int)(v - target) >= 0) && ++spin < (1 << 18));
    fence_acquire();
}
__device__ __forceinline__ void grid_arrive(unsigned* c) {
    fence_release();
    asm volatile("red.relaxed.gpu.global.add.u32 [%0], 1;" ::"l"(c) : "memory");
}

#define TMAP(n) ([] { const CUtensorMap* p_; asm volatile("{\n.reg .b64 t;\nmov.b64 t, fused_kernel_param_" #n ";\ncvta.param.u64 %0, t;\n}" : "=l"(p_)); return p_; }())
extern "C" __global__ void __launch_bounds__(384, 1)
fused_kernel(const __grid_constant__ CUtensorMap mX0, const __grid_constant__ CUtensorMap mX1, const __grid_constant__ CUtensorMap mW,
             const __grid_constant__ CUtensorMap mWr,
             const __grid_constant__ CUtensorMap mRes0, const __grid_constant__ CUtensorMap mRes1, const __grid_constant__ CUtensorMap mOut,
             const __grid_constant__ CUtensorMap mWo, bf16* __restrict__ out, const SsmParams sp) {
    extern __shared__ __align__(1024) char smraw[];
    __shared__ __align__(8) Bars s_bar[2];
    __shared__ __align__(16) float s_cs[240], s_mean[2][64], s_rstd[2][72];
    __shared__ KgShared s_kg;
    __shared__ uint32_t s_epoch;
    const uint32_t sb = s2u(smraw);
    int tid, warp, lane, bx, rank, blk, hg, npair, pair0, rot, c0;
    auto indices = [&] {
        asm volatile("mov.u32 %0, %%tid.x;" : "=r"(tid));
        asm volatile("mov.u32 %0, %%ctaid.x;" : "=r"(bx));
        warp = __shfl_sync(~0u, tid >> 5, 0); lane = tid & 31;
        rank = bx & 1; blk = bx & 15; hg = bx >> 4;
        npair = 3 - rank; pair0 = 5 * (bx >> 1) + 3 * rank;
        const int u = ((blk >> 1) + hg) & 7;
        rot = (5 * u) >> 2; c0 = 16 * (u & 3);
    };
    indices();
    TS_DECL;
    TS_BEGIN;
    KgParams kp;
    kgen_load(kp, bx * 5, warp, lane, sp);
    const uint32_t epoch0 = ldg32(&g_epoch);
#define EPOCH lds32(s2u(&s_epoch))
    if (tid < 64) g_sums[0][0][64 * bx + tid] = 0.f;
    if (tid >= 64) stg128(&g_halo[bx][0][0][0] + tid - 64, make_uint4(0, 0, 0, 0));
    if (tid < 6) s_kg.kmax[tid] = 0u;
    if (tid == 256) { prefetch_tmap(TMAP(2)); prefetch_tmap(TMAP(3)); prefetch_tmap(TMAP(0)); prefetch_tmap(TMAP(7)); }
    if (tid == 320) { prefetch_tmap(TMAP(4)); prefetch_tmap(TMAP(6)); prefetch_tmap(TMAP(1)); prefetch_tmap(TMAP(5)); }
    if (tid < 260) sts128(sb + Q_ZERO + tid * 16, make_uint4(0, 0, 0, 0));
    if (elect_one()) {
#define BAR_IS(f) (i == offsetof(Bars, f) / 8)
#pragma unroll 1
        for (int i = warp; i < NBAR; i += 12) {
            const int cnt = (i >= 4 && i < 8) ? 16 : (BAR_IS(go) || BAR_IS(att1)) ? 4 : (BAR_IS(qdone) || BAR_IS(att)) ? 8 : BAR_IS(prep) ? 96 : BAR_IS(hdone) ? 6 : BAR_IS(fdone) ? npair : BAR_IS(kdone) ? 2 : 1;
            mbar_init(s2u(s_bar) + i * 8, cnt);
            mbar_init(s2u(s_bar) + (NBAR + i) * 8, cnt);
        }
        fence_mbar_init();
    }
    __syncwarp();
    TS(29);
    fence_async_smem();
    TS(30);
    __syncthreads();
    TS(31);
    cluster_arrive_relaxed();
    cluster_wait();
    TS(27);

    int layer = 0;
    uint32_t bars = s2u(s_bar);
#define BAR(f) (bars + (uint32_t)offsetof(Bars, f))
    auto chunk = [&](int it) { return Q_ROT ? it + rot - (it + rot >= 10 ? 10 : 0) : it < 2 ? rot + it : it - 2 < rot ? it - 2 : it; };
    auto osrc_of = [&](int j) { return O_ROT ? (hg + j) & 7 : j == 0 ? hg : j - 1 < hg ? j - 1 : j; };
    auto issue_w = [&](uint32_t bb, int it, int half) {
        const int s = it & (Q_ST - 1);
        const uint32_t fb = bb + 8 * s, db = sb + s * Q_SB + Q_AB + half * 15360;
        const int k0 = chunk(it) * 64 + half * 32;
#pragma unroll
        for (int p = 0; p < 3; p++) tma2d_mc(db + p * 4096, TMAP(2), p * DM + hg * 80, k0, fb, 3);
        tma3d_mc(db + 12288, TMAP(3), hg * 80 + 64, k0, 0, fb, 3);
    };
    auto issue_x = [&](int it) {
        const int s = it & (Q_ST - 1), kc = chunk(it);
        mbar_expect(BAR(full) + 8 * s, Q_SB);
        tma3d(sb + s * Q_SB, TMAP(0) + layer, (layer ? blk : kc) * 64, (layer ? kc : blk) * 64, 0, BAR(full) + 8 * s);
    };
    {
        if (warp == 8) {
            if (elect_one()) {
#pragma unroll 1
                for (int it = 0; it < 2; it++) { issue_w(BAR(full), it, rank); issue_x(it); }
                mbar_expect(BAR(idx), 4096 + 6400);
                bulk_g2s(sb + Q_KDUMP + KG_IDX, c_fft + 16 * 512, 4096, BAR(idx));
                asm volatile("cp.async.bulk.tensor.4d.shared::cluster.global.mbarrier::complete_tx::bytes [%0], [%1, {0, 0, %3, %4}], [%2];"
                             ::"r"(sb + Q_WOT), "l"(TMAP(7)), "r"(BAR(idx)), "r"(10 * hg), "r"(5 * blk) : "memory");
                prefetch_l2((const char*)c_fft + bx * (sizeof(c_fft) / 128), sizeof(c_fft) / 128);
            }
            __syncwarp();
        }
        kgen_tables(kp, sb + Q_KG, sb + Q_KDUMP, &s_kg, warp, lane, [&] {
            if (tid == 256) s_epoch = epoch0;
        } TS_PASS);
        if (warp <= 8) asm volatile("bar.arrive 8, 384;" ::: "memory");
        fence_async_smem();
        cluster_arrive_relaxed();
        TS(1);
    }

#pragma unroll 1
    for (; layer < 2; layer++, bars += sizeof(Bars)) {
    indices();
    TS_PHASE(2 * layer);
    uint4 fa1[4], ftw[4];
    auto conv_tables = [&] {
#pragma unroll
        for (int i = 0; i < 4; i++) { fa1[i] = ldg_tab(i, tid & 127); ftw[i] = ldg_tab(8 + i, tid & 127); }
    };
    if (warp >= 8) {
        asm volatile("setmaxnreg.dec.sync.aligned.u32 88;");
        if (warp == 8) {
            if (layer == 0) {
                cluster_wait();
            } else {
                grid_wait(g_bar[2][0], 10, 32 * (EPOCH + 1), lane);
                mbar_wait(BAR(fdone) - sizeof(Bars), 0);
                fence_async_global();
                TS(1);
            }
            if (elect_one()) {
#pragma unroll 1
                for (int it = layer ? 0 : 2; it < 10; it++) {
                    if (it >= Q_ST) mbar_wait(BAR(empty) + 8 * (it & (Q_ST - 1)), ((it >> 2) - 1) & 1);
                    else if (it > 0 && Q_WAITFOR(it) >= 0) mbar_wait(BAR(full) + 8 * Q_WAITFOR(it), 0);
                    if (it == Q_ST) mbar_wait(BAR(hdone), 0);
                    issue_x(it);
                    if (it >= Q_ST || layer == 0) issue_w(BAR(full), it, rank);
                }
                if (layer == 0) { mbar_wait(BAR(prep), 0); fence_async_global(); }
#pragma unroll 1
                for (int j = 0; j < 8; j++) {
                    const int b = (j + 1) >> 2;
                    const uint32_t fb = BAR(wfull) + 8 * b;
                    if (j == 0 || j == 3 || j == 7) {
                        mbar_wait(BAR(empty) + 8 * ((2 + b) & 3), b < 2);
                        TS(11 + b);
                        mbar_expect(fb, (b == 0 ? 3 : b == 1 ? 4 : 1) * 12800);
                    }
                    bulk_g2s_mc(sb + w_grp(j) + rank * 6400, &g_wop[hg][osrc_of(j) * 10 + rank * 5], 6400, fb, 3);
                }
                mbar_expect(BAR(res), 20480);
                if (layer == 0) tma3d(sb + W_RES, TMAP(0), hg * 80, blk * 64, 0, BAR(res));
                tma3d(sb + W_RES + (layer ? 0 : 16384), TMAP(4) + layer, layer ? blk * 64 : hg * 80 + 64, layer ? hg * 80 : blk * 64, 0, BAR(res));
                if (layer == 0) { mbar_wait(BAR(kdone), 0); fence_async_global(); }
                mbar_wait(BAR(att), 0);
                fence_async_smem();
                mbar_expect(BAR(kf), (npair + 1 - layer) * 8192);
                bulk_g2s(sb + F_EO, g_keo[pair0], npair * 8192, BAR(kf));
                if (layer == 0) bulk_g2s(sb + F_S23, c_fft + 18 * 512, 8192, BAR(kf));
            }
            __syncwarp();
        } else {
            const int ht = tid - 288, hw = warp - 9, mi = lane >> 3, mj = lane & 7, g = lane >> 2, q = lane & 3;
            auto F = [](uint32_t x) { return __uint_as_float(x); };
            auto U = [](float x) { return __float_as_uint(x); };
            const uint32_t lb = layer ^ 1, eb = ~EPOCH & 1u;
            if (layer == 0) {
                mbar_wait(BAR(idx), 0);
                if (hw == 2 && elect_one()) {
                    bulk_s2g(&g_wop[hg][5 * blk], sb + Q_WOT, 6400);
#pragma unroll 1
                    for (int i = 0; i < 5; i++) bulk_s2g((char*)g_fin + (bx * 5 + i) * (FP * 2), sb + Q_ZERO, FP * 2);
                    bulk_commit();
                }
                __syncwarp();
            }
            mbar_wait(BAR(full), 0);
            mbar_wait(BAR(full) + 8, 0);
            if (ht == 0) TSX(2, 2);
            if (layer == 0) {
                float cs[2][4] = {{0.f, 0.f, 0.f, 0.f}, {0.f, 0.f, 0.f, 0.f}};
#pragma unroll
                for (int G = 0; G < 5; G++) {
                    const int row = c0 + 40 * rank + 8 * G + mj;
                    const uint32_t b = sb + (row >> 6) * Q_SB + Q_AB + ((row >> 5) & 1) * 15360;
                    uint32_t r[10];
                    ldsm_x4_t(r[0], r[1], r[2], r[3], b + hw * 4096 + (row & 31) * 128 + ((mi ^ mj) << 4));
                    ldsm_x4_t(r[4], r[5], r[6], r[7], b + hw * 4096 + (row & 31) * 128 + (((4 + mi) ^ mj) << 4));
                    ldsm_x2_t(r[8], r[9], b + 12288 + hw * 1024 + (row & 31) * 32 + (((mi & 1) ^ (mj >> 2)) << 4));
#pragma unroll
                    for (int f = 0; f < 10; f += 2) {
                        const uint32_t a = g == (f & 7) ? 0x3F803F80u : 0u, c = g == (f & 7) + 1 ? 0x3F803F80u : 0u;
                        mma16816(cs[(f >> 1) & 1], f < 8 ? a : 0u, f < 8 ? 0u : a, f < 8 ? c : 0u, f < 8 ? 0u : c, r[f], r[f + 1]);
                    }
                }
                st_ll4(&g_csp[hg][blk][ht], (U(cs[0][0] + cs[1][0]) & ~1u) | eb, U(cs[0][1] + cs[1][1]), U(cs[0][2] + cs[1][2]), U(cs[0][3] + cs[1][3]));
            }
            uint32_t xf[3][20];
#pragma unroll
            for (int i = 0; i < 3; i++) {
                const int tile = min(hw + 3 * i, 7);
#pragma unroll
                for (int k = 0; k < 5; k++) {
                    const int ch = c0 + 16 * k + 8 * (mi >> 1), tok = 16 * (tile & 3) + 8 * (mi & 1);
                    const uint32_t a = sb + (ch >> 6) * Q_SB + (tile >> 2) * 8192;
                    if (layer == 0) ldsm_x4(xf[i][4 * k], xf[i][4 * k + 1], xf[i][4 * k + 2], xf[i][4 * k + 3], a + (tok + mj) * 128 + ((((ch & 63) >> 3) ^ mj) << 4));
                    else ldsm_x4_t(xf[i][4 * k], xf[i][4 * k + 1], xf[i][4 * k + 2], xf[i][4 * k + 3], a + ((ch & 63) + mj) * 128 + (((tok >> 3) ^ mj) << 4));
                }
            }
            fence_async_smem();
            __syncwarp();
            if (lane == 0) { mbar_arrive_cta(BAR(hdone), 0); mbar_arrive_cta(BAR(hdone), 1); }
            if (ht == 0) TSX(2, 3);
            if (layer == 0) {
                if (hw == 2 && elect_one()) { bulk_wait(); fence_async_global(); grid_arrive(g_bar[3][hg]); }
                __syncwarp();
                cluster_wait();
                named_bar(8, 384);
            }
            if (ht == 0) TSX(2, 8);
#pragma unroll
            for (int i = 0; i < 3; i++) {
                float a[4] = {0.f, 0.f, 0.f, 0.f};
#pragma unroll
                for (int j = 0; j < 20; j++) {
                    const float lo = bf_lo(xf[i][j]), hi = bf_hi(xf[i][j]);
                    a[2 * (j & 1)] += lo + hi; a[2 * (j & 1) + 1] = fmaf(lo, lo, fmaf(hi, hi, a[2 * (j & 1) + 1]));
                }
#pragma unroll
                for (int j = 0; j < 4; j++) { a[j] += __shfl_xor_sync(~0u, a[j], 1); a[j] += __shfl_xor_sync(~0u, a[j], 2); }
                if (q == 0 && hw + 3 * i < 8) st_ll4(&g_stp[blk][hg][8 * (hw + 3 * i) + g], (U(a[0]) & ~1u) | lb, U(a[1]), U(a[2]), U(a[3]));
            }
            if (ht == 0) TSX(2, 4);
            if (layer == 0) {
                float t[4] = {0.f, 0.f, 0.f, 0.f};
                uint4 v[16];
                int spin = 0;
                uint32_t bad;
                do {
                    bad = 0;
#pragma unroll
                    for (int j = 0; j < 16; j++) v[j] = ld_ll4(&g_csp[hg][j][ht]);
#pragma unroll
                    for (int j = 0; j < 16; j++) bad |= v[j].x ^ eb;
                } while ((bad & 1u) && ++spin < (1 << 18));
#pragma unroll
                for (int j = 0; j < 16; j++) { t[0] += F(v[j].x); t[1] += F(v[j].y); t[2] += F(v[j].z); t[3] += F(v[j].w); }
                *(float2*)&s_cs[80 * hw + 20 * q + 2 * g] = make_float2(t[0], t[1]);
                if (g < 2) *(float2*)&s_cs[80 * hw + 20 * q + 16 + 2 * g] = make_float2(t[2], t[3]);
                if (hw == 2) grid_wait(g_bar[3][0], 8, 16 * (EPOCH + 1), lane);
            }
            if (ht == 0) TSX(2, 15);
            if (ht < 80) {
                const bool halo = ht >= 64;
                const int p = halo ? (ht >> 3) & 1 : ht >> 5, i = halo ? (ht & 7) - 8 : 8 + 2 * (ht & 24) + (ht & 7);
                const uint4* src = &g_stp[halo && blk ? blk - 1 : blk][0][halo ? 32 * p + 24 + (ht & 7) : ht];
                uint4 v[8];
                int spin = 0;
                uint32_t bad;
                do {
                    bad = 0;
#pragma unroll
                    for (int j = 0; j < 8; j++) v[j] = ld_ll4(src + 64 * j);
#pragma unroll
                    for (int j = 0; j < 8; j++) bad |= v[j].x ^ lb;
                } while ((bad & 1u) && ++spin < (1 << 18));
                float t[4] = {0.f, 0.f, 0.f, 0.f};
#pragma unroll
                for (int j = 0; j < 8; j++) { t[0] += F(v[j].x); t[1] += F(v[j].y); t[2] += F(v[j].z); t[3] += F(v[j].w); }
                const uint32_t s0 = ln_finish_packed(t[0], t[1]), s1 = ln_finish_packed(t[2], t[3]);
                if (!halo) { s_mean[p][i - 8] = bf_hi(s0); s_mean[p][i] = bf_hi(s1); s_rstd[p][i] = frcp(bf_lo(s0)); }
                s_rstd[p][i + 8] = frcp(bf_lo(s1));
            }
            fence_acquire();
            mbar_arrive(BAR(prep));
            if (ht == 0) TSX(2, 5);
            if (layer == 0) {
                __syncwarp();
                kgen_expand(bx * 5, sb + Q_KDUMP, &s_kg, ht TS_PASS);
                fence_async_smem();
                named_bar(4, 96);
                if (ht == 0) { fence_release(); mbar_arrive_cta(BAR(kdone), 0); mbar_arrive_cta(BAR(kdone), 1); }
                if (ht == 0) TSX(2, 7);
            }
        }
        __syncwarp();
        named_bar(3, 128);
        conv_tables();
        asm volatile("setmaxnreg.inc.sync.aligned.u32 168;");
    } else {
    const int wg = warp >> 2, w = warp & 3;
    const int mi = lane >> 3, mj = lane & 7, g = lane >> 2, q = lane & 3;
    TS(2);
    float acc[120];
#pragma unroll
    for (int i = 0; i < 120; i++) acc[i] = 0.f;
    auto release = [&](int it) {
        if (lane == 0) { mbar_arrive_cta(BAR(empty) + 8 * (it & (Q_ST - 1)), 0); mbar_arrive_cta(BAR(empty) + 8 * (it & (Q_ST - 1)), 1); }
    };
#pragma unroll 1
    for (int it = 0; it < 10; it++) {
        const int s = it & (Q_ST - 1);
        const uint32_t st = sb + s * Q_SB;
        const bool hold = wg == 1 && it == Q_S0;
        if (hold) {
            wg_wait<0>();
            release(it - 1);
            mbar_wait(BAR(go), 0);
        }
        mbar_wait(BAR(full) + 8 * (s), (it >> 2) & 1);
        if (it < 2) TS(3 + it);
        if (it == 6) TS(5);
        if (it == 9) TS(6);
        const uint64_t da = mkdesc(st + wg * 8192, 16, 1024, 1);
        const uint64_t db = mkdesc(st + Q_AB, 4096, 1024, 1);
        const uint64_t dr = mkdesc(st + Q_AB + 12288, 1024, 256, 3);
        if (layer == 0) {
            wg_fence();
#pragma unroll
            for (int ks = 0; ks < 4; ks++) {
                const int sc = 1;
                wgmma_n192<0, 1>(*(float(*)[96]) & acc[0], da + ks * 2, db + (ks >> 1) * 960 + (ks & 1) * 128, sc);
                wgmma_n48<0, 1>(*(float(*)[24]) & acc[96], da + ks * 2, dr + (ks >> 1) * 960 + (ks & 1) * 32, sc);
            }
            wg_commit();
        } else {
            wg_fence();
#pragma unroll
            for (int ks = 0; ks < 4; ks++) {
                const int sc = 1;
                wgmma_n192<1, 1>(*(float(*)[96]) & acc[0], da + ks * 128, db + (ks >> 1) * 960 + (ks & 1) * 128, sc);
                wgmma_n48<1, 1>(*(float(*)[24]) & acc[96], da + ks * 128, dr + (ks >> 1) * 960 + (ks & 1) * 32, sc);
            }
            wg_commit();
        }
        wg_wait<1>();
        if (it > 0 && !hold) release(it - 1);
    }
    if (wg == 0 && lane == 0) mbar_arrive(BAR(go));
    asm volatile("setmaxnreg.inc.sync.aligned.u32 208;");
    if (layer == 0) cluster_wait();
    mbar_wait(BAR(prep), 0);
    const uint32_t ob = layer ^ 1;
    const bool first = (blk == 0 && w == 0);
    const bool sel0 = (2 * q > g), sel1 = (2 * q + 1 > g);
    constexpr float SC = 0.22360679774997896f * 1.4426950408889634f;
    const float m0 = s_mean[wg][16 * w + g], m1 = s_mean[wg][8 + 16 * w + g];
    const float* rs = &s_rstd[wg][16 * w];
    const float kx0 = rs[2 * q + (sel0 ? 0 : 8)], kx1 = rs[2 * q + (sel1 ? 1 : 9)], ky0 = rs[2 * q + (sel0 ? 8 : 16)], ky1 = rs[2 * q + (sel1 ? 9 : 17)];
    const float cx0 = SC * rs[8 + g] * kx0, cx1 = SC * rs[8 + g] * kx1, cy0 = SC * rs[16 + g] * ky0, cy1 = SC * rs[16 + g] * ky1;
    uint4 cs[3][5];
    auto cs_load = [&](int p) {
#pragma unroll
        for (int i = 0; i < 5; i++) cs[p][i] = lds128(s2u(&s_cs[80 * p + 20 * q + 4 * i]));
    };
    cs_load(1); cs_load(2);
    wg_wait<0>();
    TS(7);
    if (lane == 0) mbar_arrive(BAR(qdone));
    uint32_t ql[10], qh[10], kl[10], kh[10], vl[10], vh[10];
    auto fold = [&](int p, int f, int h) {
        const int j = (f < 8) ? 8 * p + f : 24 + 2 * p + (f - 8);
        const float c0 = __uint_as_float(u4(cs[p][f >> 1], 2 * (f & 1))), c1 = __uint_as_float(u4(cs[p][f >> 1], 2 * (f & 1) + 1));
        const float m = h ? m1 : m0;
        return pack2(fmaf(-m, c0, acc[4 * j + 2 * h]), fmaf(-m, c1, acc[4 * j + 2 * h + 1]));
    };
#pragma unroll
    for (int f = 0; f < 10; f++) { kh[f] = fold(1, f, 1); vh[f] = fold(2, f, 1); }
    if (w == 3) {
        uint4* hp = &g_halo[bx][wg][0][lane];
        st_ll4(hp, (kh[0] & ~1u) | ob, kh[1], kh[3], kh[4]); st_ll4(hp + 32, (kh[5] & ~1u) | ob, kh[6], kh[8], kh[9]);
        st_ll4(hp + 64, (vh[0] & ~1u) | ob, vh[1], vh[2], vh[3]); st_ll4(hp + 96, (vh[4] & ~1u) | ob, vh[5], vh[6], vh[7]);
        st_ll4(hp + 128, (vh[8] & ~1u) | ob, vh[9], kh[2], kh[7]);
    } else {
        const uint32_t a = sb + Q_EOFF + (warp - wg) * Q_ESLOT + mj * Q_EROW + mi * 16;
        stsm_x4(a, kh[0], kh[1], kh[3], kh[4]);
        stsm_x4(a + 64, kh[5], kh[6], kh[8], kh[9]);
        stsm_x4(a + 128, vh[0], vh[1], vh[2], vh[3]);
        stsm_x4(a + 192, vh[4], vh[5], vh[6], vh[7]);
        stsm_x4(a + 256, vh[8], vh[9], kh[2], kh[7]);
        __syncwarp();
        if (lane == 0) mbar_arrive(BAR(ex) + 8 * warp);
    }
    TS(9);
    cs_load(0);
#pragma unroll
    for (int f = 0; f < 10; f++) { kl[f] = fold(1, f, 0); vl[f] = fold(2, f, 0); }
#pragma unroll
    for (int f = 0; f < 10; f++) { ql[f] = fold(0, f, 0); qh[f] = fold(0, f, 1); }
    uint4 hv[5];
    const uint4* hp = &g_halo[bx - 1][wg][0][lane];
    auto prev = [&] {
        if (w > 0) {
            const uint32_t a = sb + Q_EOFF + (warp - wg - 1) * Q_ESLOT + mj * Q_EROW + mi * 16;
            mbar_wait(BAR(ex) + 8 * (warp - 1), 0);
            ldsm_x4(hv[0].x, hv[0].y, hv[0].z, hv[0].w, a);
            ldsm_x4(hv[1].x, hv[1].y, hv[1].z, hv[1].w, a + 64);
            ldsm_x4_t(hv[2].x, hv[2].y, hv[2].z, hv[2].w, a + 128);
            ldsm_x4_t(hv[3].x, hv[3].y, hv[3].z, hv[3].w, a + 192);
            ldsm_x2_t(hv[4].x, hv[4].y, a + 256);
            ldsm_x2(hv[4].z, hv[4].w, a + 288 - (lane >> 4) * 32);
        } else if (blk > 0) {
#pragma unroll
            for (int f = 0; f < 5; f++) hv[f] = ld_ll4(hp + 32 * f);
        } else {
#pragma unroll
            for (int f = 0; f < 5; f++) hv[f] = make_uint4(0, 0, 0, 0);
        }
    };
    if (A_HPOS == 0) prev();
    uint32_t vt[10][2];
#pragma unroll
    for (int f = 0; f < 10; f++) { vt[f][0] = movm_t(vl[f]); vt[f][1] = movm_t(vh[f]); }
    if (A_HPOS == 1) prev();
    TS(10);
    auto FA = [](int h) { return h == 0 ? 0 : h == 1 ? 3 : h == 2 ? 5 : 8; };
    auto FH = [](int h) { return h < 2 ? 2 : 7; };
    const uint32_t pm = (sel0 ? 0xFFFFu : 0u) | (sel1 ? 0xFFFF0000u : 0u);
    auto softmax = [&](float x0, float x1, float k0, float k1) {
        float mx = fmaxf(x0, x1);
        mx = fmaxf(mx, __shfl_xor_sync(~0u, mx, 1));
        mx = fmaxf(mx, __shfl_xor_sync(~0u, mx, 2));
        x0 = ex2(x0 - mx); x1 = ex2(x1 - mx);
        float sx = x0 + x1;
        sx += __shfl_xor_sync(~0u, sx, 1);
        sx += __shfl_xor_sync(~0u, sx, 2);
        const float ix = frcp(sx);
        return pack2(x0 * k0 * ix, x1 * k1 * ix);
    };
    uint32_t qm[4][2], py[4];
    float sl[4][2];
#pragma unroll
    for (int h = 0; h < 4; h++) {
        const int fa = FA(h), fb = fa + 1, fh = FH(h);
        const bool mine = (h & 1) ? (q >= 2) : (q < 2);
        qm[h][0] = mine ? ql[fh] : 0u; qm[h][1] = mine ? qh[fh] : 0u;
        float S1[4] = {0.f, 0.f, 0.f, 0.f}, S2[4] = {0.f, 0.f, 0.f, 0.f};
        mma16816(S1, ql[fa], qh[fa], ql[fb], qh[fb], kl[fa], kl[fb]); mma1688(S1, qm[h][0], qm[h][1], kl[fh]);
        mma16816(S2, ql[fa], qh[fa], ql[fb], qh[fb], kh[fa], kh[fb]); mma1688(S2, qm[h][0], qm[h][1], kh[fh]);
        sl[h][0] = S1[0]; sl[h][1] = S1[1];
        py[h] = softmax((sel0 ? S1[2] : S2[2]) * cy0, (sel1 ? S1[3] : S2[3]) * cy1, ky0, ky1);
    }
    TS(11);
    if (w == 0 && blk > 0) {
        int spin = 0;
        while (__any_sync(~0u, ((hv[0].x ^ ob) | (hv[1].x ^ ob) | (hv[2].x ^ ob) | (hv[3].x ^ ob) | (hv[4].x ^ ob)) & 1u) && ++spin < (1 << 18)) {
#pragma unroll
            for (int f = 0; f < 5; f++) hv[f] = ld_ll4(hp + 32 * f);
        }
#pragma unroll
        for (int f = 2; f < 4; f++) hv[f] = make_uint4(movm_t(hv[f].x), movm_t(hv[f].y), movm_t(hv[f].z), movm_t(hv[f].w));
        hv[4].x = movm_t(hv[4].x); hv[4].y = movm_t(hv[4].y);
    }
    const uint32_t kp[10] = {hv[0].x, hv[0].y, hv[4].z, hv[0].z, hv[0].w, hv[1].x, hv[1].y, hv[4].w, hv[1].z, hv[1].w};
    const uint32_t vp[10] = {hv[2].x, hv[2].y, hv[2].z, hv[2].w, hv[3].x, hv[3].y, hv[3].z, hv[3].w, hv[4].x, hv[4].y};
    TS(12);
    const float bx0 = first && sel0 ? -INFINITY : 0.f, bx1 = first && sel1 ? -INFINITY : 0.f;
    float oacc[10][4];
#pragma unroll
    for (int h = 0; h < 4; h++) {
        const int fa = FA(h), fb = fa + 1, fh = FH(h);
        const bool mine = (h & 1) ? (q >= 2) : (q < 2);
        float S0[4] = {0.f, 0.f, 0.f, 0.f};
        mma16816(S0, ql[fa], qh[fa], ql[fb], qh[fb], kp[fa], kp[fb]); mma1688(S0, qm[h][0], qm[h][1], kp[fh]);
        const uint32_t px = softmax(fmaf(sel0 ? S0[0] : sl[h][0], cx0, bx0), fmaf(sel1 ? S0[1] : sl[h][1], cx1, bx1), kx0, kx1);
#pragma unroll
        for (int i = 0; i < 3; i++) {
            const int f = (i == 0) ? fa : (i == 1) ? fb : fh;
            float O[4] = {0.f, 0.f, 0.f, 0.f};
            mma16816(O, px & ~pm, py[h] & pm, 0u, py[h] & ~pm, vt[f][0], vt[f][1]);
            mma1688(O, px & pm, 0u, vp[f]);
            if (i < 2 || !(h & 1) || mine) { oacc[f][0] = O[0]; oacc[f][1] = O[1]; oacc[f][2] = O[2]; oacc[f][3] = O[3]; }
        }
    }
    TS(13);
    uint4 of[7][5];
    {
        uint4* dst = &g_of[hg][blk][warp][0][lane];
#pragma unroll
        for (int k = 0; k < 5; k++) {
            of[0][k] = make_uint4((pack2(oacc[2 * k][0], oacc[2 * k][1]) & ~1u) | ob, pack2(oacc[2 * k][2], oacc[2 * k][3]),
                                  pack2(oacc[2 * k + 1][0], oacc[2 * k + 1][1]), pack2(oacc[2 * k + 1][2], oacc[2 * k + 1][3]));
            st_ll4(dst + 32 * k, of[0][k].x, of[0][k].y, of[0][k].z, of[0][k].w);
        }
    }
    if (Q_WGATE && wg == 1 && lane == 0) mbar_arrive(BAR(att1));
    TS(14);
    const uint4* osrc = &g_of[0][blk][warp][0][lane];
    auto oload = [&](int j) {
        const uint4* p = osrc + osrc_of(j) * 20480;
#pragma unroll
        for (int k = 0; k < 5; k++) of[j % 7][k] = ld_ll4(p + 32 * k);
    };
    float aw[40];
    auto omma = [&](int j) {
        const uint64_t dm = mkdesc(sb + w_grp(j), 1280, 128, 0);
        wg_fence();
#pragma unroll
        for (int k = 0; k < 5; k++) wgmma_rs80(aw, of[j % 7][k], dm + k * 160, j + k > 0);
        wg_commit();
    };
    if (Q_WGATE && wg == 0) mbar_wait(BAR(att1), 0);
    mbar_wait(BAR(wfull), 0);
    omma(0);
    TS(8);
    {
        const uint32_t* pp = &g_of[osrc_of(1 + min(lane, 6))][blk][warp][4][31].x;
        uint32_t v, m;
        int spin = 0;
        do {
            asm volatile("ld.relaxed.gpu.global.u32 %0, [%1];" : "=r"(v) : "l"(pp) : "memory");
            m = __ballot_sync(~0u, (v & 1u) != ob);
        } while ((m & O_MASK) && ++spin < (1 << 18));
        TS(15);
        if (O_GATE) named_bar(O_GATE == 1 ? 1 + wg : 9, O_GATE == 1 ? 128 : 256);
#pragma unroll
        for (int j = 1; j <= O_DEPTH; j++) oload(j);
        wg_wait<0>();
        TS(16);
    }
#pragma unroll
    for (int j = 1; j < 8; j++) {
        if (j == 3 || j == 7) mbar_wait(BAR(wfull) + 8 * ((j + 1) >> 2), 0);
        int spin = 0;
        while (true) {
            const uint4* f = of[j % 7];
            const uint32_t bad = ((f[0].x ^ ob) | (f[1].x ^ ob) | (f[2].x ^ ob) | (f[3].x ^ ob) | (f[4].x ^ ob)) & 1u;
            if (__all_sync(~0u, !bad) || ++spin >= (1 << 18)) break;
            oload(j);
        }
        if (j + O_DEPTH < 8) oload(j + O_DEPTH);
        if (j == 1) TS(17);
        if (j == 5) TS(18);
        omma(j);
        if (j == O_KAT && lane == 0) mbar_arrive(BAR(att));
    }
    wg_wait<2>();
    uint32_t res[20];
    mbar_wait(BAR(res), 0);
    const uint32_t ta = (8 * (mi >> 1) + mj) * 128 + (((2 * w + (mi & 1)) ^ mj) << 4);
    if (layer == 0) {
        const int tok = 16 * w + 8 * (mi & 1) + mj;
#pragma unroll
        for (int k = 0; k < 4; k++)
            ldsm_x4(res[4 * k], res[4 * k + 1], res[4 * k + 2], res[4 * k + 3], sb + W_RES + wg * 8192 + tok * 128 + (((2 * k + (mi >> 1)) ^ mj) << 4));
        ldsm_x4(res[16], res[17], res[18], res[19], sb + W_RES + 16384 + wg * 2048 + tok * 32 + (((mi >> 1) ^ (mj >> 2)) << 4));
    } else {
#pragma unroll
        for (int k = 0; k < 5; k++) ldsm_x4_t(res[4 * k], res[4 * k + 1], res[4 * k + 2], res[4 * k + 3], sb + W_RES + wg * 10240 + k * 2048 + ta);
    }
    mbar_wait(BAR(qdone), 0);
    wg_wait<0>();
    TS(19);
#pragma unroll
    for (int i = 0; i < 20; i++) {
        const uint32_t y = pack2(aw[2 * i], aw[2 * i + 1]);
        asm("add.rn.bf16x2 %0, %0, %1;" : "+r"(res[i]) : "r"(y));
    }
#pragma unroll
    for (int k = 0; k < 5; k++) stsm_x4_t(sb + W_OUT + wg * 10240 + k * 2048 + ta, res[4 * k], res[4 * k + 1], res[4 * k + 2], res[4 * k + 3]);
    fence_async_smem();
    named_bar(1 + wg, 128);
    if (w == 0 && elect_one()) {
        asm volatile("cp.async.bulk.tensor.2d.global.shared::cta.bulk_group [%0, {%2, %3}], [%1];"
                     ::"l"(TMAP(6)), "r"(sb + W_OUT + wg * 10240), "r"(1024 * wg + 64 * blk), "r"(hg * 80) : "memory");
        bulk_commit();
    }
    __syncwarp();
    conv_tables();
    TS(20);
    {
        float sm[4] = {0.f, 0.f, 0.f, 0.f}, d0[4] = {0.f, 0.f, 0.f, 0.f}, d1[4] = {0.f, 0.f, 0.f, 0.f};
#pragma unroll
        for (int k = 0; k < 5; k++) {
            mma16816(sm, res[4 * k], res[4 * k + 1], res[4 * k + 2], res[4 * k + 3], 0x3F803F80u, 0x3F803F80u);
            mma16816(d0, res[4 * k], res[4 * k + 1], res[4 * k + 2], res[4 * k + 3], res[4 * k], res[4 * k + 2]);
            mma16816(d1, res[4 * k], res[4 * k + 1], res[4 * k + 2], res[4 * k + 3], res[4 * k + 1], res[4 * k + 3]);
        }
        const bool diag = q == (g >> 1);
        if (diag || q == ((g >> 1) ^ 1)) {
            float* dst = g_sums[layer][diag] + 1024 * wg + 64 * blk + 16 * w + g;
            asm volatile("red.global.add.f32 [%0], %1;" ::"l"(dst), "f"(diag ? ((g & 1) ? d0[1] : d0[0]) : sm[0]) : "memory");
            asm volatile("red.global.add.f32 [%0], %1;" ::"l"(dst + 8), "f"(diag ? ((g & 1) ? d1[3] : d1[2]) : sm[2]) : "memory");
        }
    }
    TS(21);
    named_bar(1 + wg, 128);
    asm volatile("setmaxnreg.dec.sync.aligned.u32 168;");
    TS(22);
    }
    TS_PHASE(2 * layer + 1);
    TS(0);
    indices();
    const int wg = warp >> 2;
    if (wg < npair) {
        conv_pair(2 * (pair0 + wg), layer, sb + F_EO + wg * 8192, sb + wg * Q_SB, sb + F_S23, BAR(kf), warp, lane, fa1, ftw, [&] {
            if (wg < 2 && (warp & 3) == 0 && elect_one()) { bulk_wait(); fence_async_global(); grid_arrive(g_bar[layer][hg]); }
            __syncwarp();
        }, [&] {
            if (warp == 0) {
                grid_wait(g_bar[layer][0], 8, 32 * (EPOCH + 1), lane);
                if (lane == 0) mbar_arrive(BAR(ardy));
            } else {
                mbar_wait(BAR(ardy), 0);
            }
        } TS_PASS);
        if (layer == 0) {
            named_bar(1 + wg, 128);
            if ((tid & 127) == 0) { mbar_arrive(BAR(fdone)); grid_arrive(g_bar[2][(pair0 + wg) >> 5]); }
            __syncwarp();
        }
    } else if (layer == 0 && warp == 8) {
        mbar_wait(BAR(ardy), 0);
        const long long t0 = clock64();
        while (clock64() - t0 < F_WDELAY) {}
        if (elect_one()) {
#pragma unroll 1
            for (int i = 0; i < 2 * Q_ST; i++) issue_w(BAR(full) + sizeof(Bars), i >> 1, i & 1);
        }
        __syncwarp();
    }
    if (wg >= npair) named_bar(3, 128);
    TS(20);
    }
    indices();
    __syncthreads();
    if (tid < 320) {
        const int cq = (warp & ~1) + (lane & 1), tg = 16 * (warp & 1) + (lane >> 1);
        const uint4* src = (const uint4*)&g_fin[40 * hg + 4 * cq][1024 * (tg >> 4) + 64 * blk + 4 * (tg & 15)];
        uint4 v[4];
#pragma unroll
        for (int i = 0; i < 4; i++) v[i].x = 0u;
        int spin = 0;
        while (true) {
#pragma unroll
            for (int i = 0; i < 4; i++) if (v[i].x == 0u) v[i] = ld_ll4(src + i * (FP / 4));
            if ((v[0].x && v[1].x && v[2].x && v[3].x) || ++spin >= (1 << 18)) break;
            __nanosleep(FIN_SLEEP);
        }
        TS(21);
        bf16* dst = out + (size_t)(128 * blk + 8 * (tg & 15) + (tg >> 4)) * DM + 80 * hg + 8 * cq;
#pragma unroll
        for (int i = 0; i < 4; i++) stg128(dst + 2 * i * DM, make_uint4(u4(v[0], i), u4(v[1], i), u4(v[2], i), u4(v[3], i)));
    }
    if (bx == 0 && tid == 0) g_epoch = EPOCH + 1;
    TS(22);
    TS_END;
}
typedef CUresult (*EncodeTiledFn)(CUtensorMap*, CUtensorMapDataType, cuuint32_t, void*, const cuuint64_t*, const cuuint64_t*, const cuuint32_t*,
                                  const cuuint32_t*, CUtensorMapInterleave, CUtensorMapSwizzle, CUtensorMapL2promotion, CUtensorMapFloatOOBfill);

static void make_map(EncodeTiledFn enc, CUtensorMap* m, const void* base, int rank, const cuuint64_t* dims, const cuuint64_t* strides,
                     const cuuint32_t* box, CUtensorMapSwizzle sw) {
    cuuint32_t es[4] = {1, 1, 1, 1};
    enc(m, CU_TENSOR_MAP_DATA_TYPE_BFLOAT16, rank, (void*)base, dims, strides, box, es, CU_TENSOR_MAP_INTERLEAVE_NONE, sw,
        sw == CU_TENSOR_MAP_SWIZZLE_128B ? CU_TENSOR_MAP_L2_PROMOTION_L2_128B : CU_TENSOR_MAP_L2_PROMOTION_NONE, CU_TENSOR_MAP_FLOAT_OOB_FILL_NONE);
}

template <typename... KArgs, typename... Args>
static void launch(void (*kern)(KArgs...), int grid, int block, int smem, int cluster, bool pdl, Args... args) {
    cudaLaunchConfig_t cfg = {};
    cfg.gridDim = dim3(grid); cfg.blockDim = dim3(block); cfg.dynamicSmemBytes = smem; cfg.stream = cudaStreamPerThread;
    cudaLaunchAttribute at[2];
    int n = 0;
    if (cluster > 1) { at[n].id = cudaLaunchAttributeClusterDimension; at[n].val.clusterDim.x = cluster; at[n].val.clusterDim.y = 1; at[n].val.clusterDim.z = 1; n++; }
    if (pdl) { at[n].id = cudaLaunchAttributeProgrammaticStreamSerialization; at[n].val.programmaticStreamSerializationAllowed = 1; n++; }
    cfg.attrs = at; cfg.numAttrs = n;
    cudaLaunchKernelEx(&cfg, kern, KArgs(args)...);
}

struct HostState {
    bool ready = false;
    const void* key[4] = {nullptr, nullptr, nullptr, nullptr};
    CUtensorMap mX[2], mRes[2], mW, mWr, mWo, mOut;
    bf16 *x1T, *x2T;
};

extern "C" void kernel_launch(void* const* d_in, const int* in_sizes, int n_in, void* d_out, int out_size) {
    const bf16* x = (const bf16*)d_in[0];
    const bf16* wqkv = (const bf16*)d_in[1];
    const bf16* wo = (const bf16*)d_in[2];
    const bf16* lar = (const bf16*)d_in[4];
    const bf16* aim = (const bf16*)d_in[5];
    const bf16* cre = (const bf16*)d_in[6];
    const bf16* cim = (const bf16*)d_in[7];
    const bf16* logdt = (const bf16*)d_in[8];
    const bf16* dskip = (const bf16*)d_in[9];
    static HostState hs;
    if (!hs.ready || hs.key[0] != wqkv || hs.key[1] != wo || hs.key[2] != x) {
        void* fn = nullptr;
        cudaDriverEntryPointQueryResult qr;
        cudaGetDriverEntryPoint("cuTensorMapEncodeTiled", &fn, cudaEnableDefault, &qr);
        EncodeTiledFn enc = (EncodeTiledFn)fn;
        cudaGetSymbolAddress((void**)&hs.x1T, g_x1T);
        cudaGetSymbolAddress((void**)&hs.x2T, g_x2T);
        {
            cuuint64_t d[3] = {DM, SEQ / 2, 2}, s[2] = {DM * 4, DM * 2};
            cuuint32_t b[3] = {64, 64, 2}, br[3] = {16, 64, 2};
            make_map(enc, &hs.mX[0], x, 3, d, s, b, CU_TENSOR_MAP_SWIZZLE_128B);
            make_map(enc, &hs.mRes[0], x, 3, d, s, br, CU_TENSOR_MAP_SWIZZLE_32B);
            cuuint64_t d2[3] = {SEQ / 2, DM, 2}, s2[2] = {XP * 2, SEQ};
            cuuint32_t b2[3] = {64, 80, 2};
            make_map(enc, &hs.mX[1], hs.x2T, 3, d2, s2, b, CU_TENSOR_MAP_SWIZZLE_128B);
            make_map(enc, &hs.mRes[1], hs.x2T, 3, d2, s2, b2, CU_TENSOR_MAP_SWIZZLE_128B);
            cuuint64_t d3[2] = {SEQ, DM};
            make_map(enc, &hs.mOut, hs.x1T, 2, d3, s2, b2, CU_TENSOR_MAP_SWIZZLE_128B);
        }
        { cuuint64_t d[2] = {3 * DM, DM}, s[1] = {3 * DM * 2}; cuuint32_t b[2] = {64, 32};
          make_map(enc, &hs.mW, wqkv, 2, d, s, b, CU_TENSOR_MAP_SWIZZLE_128B); }
        { cuuint64_t d[3] = {DM, DM, 3}, s[2] = {3 * DM * 2, DM * 2}; cuuint32_t b[3] = {16, 32, 3};
          make_map(enc, &hs.mWr, wqkv, 3, d, s, b, CU_TENSOR_MAP_SWIZZLE_32B); }
        { cuuint64_t d[4] = {8, 8, DM / 8, DM / 8}, s[3] = {DM * 2, 16, DM * 16}; cuuint32_t b[4] = {8, 8, 10, 5};
          make_map(enc, &hs.mWo, wo, 4, d, s, b, CU_TENSOR_MAP_SWIZZLE_NONE); }
        cudaFuncSetAttribute(fused_kernel, cudaFuncAttributeMaxDynamicSharedMemorySize, Q_SMEM);
        hs.key[0] = wqkv; hs.key[1] = wo; hs.key[2] = x;
        hs.ready = true;
    }
    const SsmParams sp = {lar, aim, cre, cim, logdt, dskip};
    launch(fused_kernel, 128, 384, Q_SMEM, 2, false, hs.mX[0], hs.mX[1], hs.mW, hs.mWr, hs.mRes[0], hs.mRes[1], hs.mOut, hs.mWo, (bf16*)d_out, sp);
}
```

```cpp
#include <cuda_runtime.h>
#include <cuda.h>
#include <cuda_bf16.h>
#include <cuda_fp16.h>
#include <stdint.h>

typedef __nv_bfloat16 bf16;

constexpr int SEQ = 2048;
constexpr int DM  = 640;
constexpr int XP  = SEQ + 64;
constexpr int NMODE = 192;

__device__ __forceinline__ uint32_t s2u(const void* p) { return (uint32_t)__cvta_generic_to_shared(p); }
__device__ __forceinline__ void mbar_init(uint32_t b, int c) { asm volatile("mbarrier.init.shared::cta.b64 [%0], %1;" ::"r"(b), "r"(c)); }
__device__ __forceinline__ void mbar_expect(uint32_t b, uint32_t bytes) { asm volatile("mbarrier.arrive.expect_tx.shared::cta.b64 _, [%0], %1;" ::"r"(b), "r"(bytes) : "memory"); }
__device__ __forceinline__ void mbar_arrive(uint32_t b) { asm volatile("mbarrier.arrive.shared::cta.b64 _, [%0];" ::"r"(b) : "memory"); }
__device__ __forceinline__ void mbar_arrive_cta(uint32_t b, uint32_t cta) {
    asm volatile("{\n.reg .b32 ra;\nmapa.shared::cluster.u32 ra, %0, %1;\nmbarrier.arrive.shared::cluster.b64 _, [ra];\n}" ::"r"(b), "r"(cta) : "memory");
}
__device__ __forceinline__ void mbar_wait(uint32_t b, uint32_t ph) {
#ifdef M_PLAIN
    asm volatile("{\n.reg .pred p;\nW: mbarrier.try_wait.parity.shared::cta.b64 p, [%0], %1;\n@!p bra W;\n}" ::"r"(b), "r"(ph) : "memory");
    return;
#endif
    asm volatile("{\n.reg .pred p;\n.reg .u32 n;\nmbarrier.try_wait.parity.shared::cta.b64 p, [%0], %1;\n@p bra D;\nmov.u32 n, 0;\n"
                 "W: mbarrier.try_wait.parity.shared::cta.b64 p, [%0], %1;\n@p bra D;\nadd.u32 n, n, 1;\nsetp.lt.u32 p, n, 4194304;\n@p bra W;\ntrap;\nD:\n}"
                 ::"r"(b), "r"(ph) : "memory");
}
__device__ __forceinline__ void fence_mbar_init() { asm volatile("fence.mbarrier_init.release.cluster;" ::: "memory"); }
__device__ __forceinline__ void cluster_sync() { asm volatile("barrier.cluster.arrive.aligned;\nbarrier.cluster.wait.aligned;" ::: "memory"); }
__device__ __forceinline__ void pdl_wait() { asm volatile("griddepcontrol.wait;" ::: "memory"); }
__device__ __forceinline__ void pdl_launch() { asm volatile("griddepcontrol.launch_dependents;" ::: "memory"); }
__device__ __forceinline__ void named_bar(int id, int n) { asm volatile("bar.sync %0, %1;" ::"r"(id), "r"(n) : "memory"); }
__device__ __forceinline__ void fence_async_smem() { asm volatile("fence.proxy.async.shared::cta;" ::: "memory"); }

__device__ __forceinline__ void tma2d(uint32_t dst, const CUtensorMap* m, int c0, int c1, uint32_t bar) {
    asm volatile("cp.async.bulk.tensor.2d.shared::cluster.global.mbarrier::complete_tx::bytes [%0], [%1, {%3, %4}], [%2];"
                 ::"r"(dst), "l"(m), "r"(bar), "r"(c0), "r"(c1) : "memory");
}
__device__ __forceinline__ void tma2d_mc(uint32_t dst, const CUtensorMap* m, int c0, int c1, uint32_t bar, uint16_t mask) {
    asm volatile("cp.async.bulk.tensor.2d.shared::cluster.global.mbarrier::complete_tx::bytes.multicast::cluster [%0], [%1, {%3, %4}], [%2], %5;"
                 ::"r"(dst), "l"(m), "r"(bar), "r"(c0), "r"(c1), "h"(mask) : "memory");
}
__device__ __forceinline__ void tma3d(uint32_t dst, const CUtensorMap* m, int c0, int c1, int c2, uint32_t bar) {
    asm volatile("cp.async.bulk.tensor.3d.shared::cluster.global.mbarrier::complete_tx::bytes [%0], [%1, {%3, %4, %5}], [%2];"
                 ::"r"(dst), "l"(m), "r"(bar), "r"(c0), "r"(c1), "r"(c2) : "memory");
}
__device__ __forceinline__ void tma3d_mc(uint32_t dst, const CUtensorMap* m, int c0, int c1, int c2, uint32_t bar, uint16_t mask) {
    asm volatile("cp.async.bulk.tensor.3d.shared::cluster.global.mbarrier::complete_tx::bytes.multicast::cluster [%0], [%1, {%3, %4, %5}], [%2], %6;"
                 ::"r"(dst), "l"(m), "r"(bar), "r"(c0), "r"(c1), "r"(c2), "h"(mask) : "memory");
}
__device__ __forceinline__ void bulk_g2s(uint32_t dst, const void* src, uint32_t bytes, uint32_t bar) {
    asm volatile("cp.async.bulk.shared::cluster.global.mbarrier::complete_tx::bytes [%0], [%1], %2, [%3];"
                 ::"r"(dst), "l"(src), "r"(bytes), "r"(bar) : "memory");
}
__device__ __forceinline__ void bulk_g2s_mc(uint32_t dst, const void* src, uint32_t bytes, uint32_t bar, uint16_t mask) {
    asm volatile("cp.async.bulk.shared::cluster.global.mbarrier::complete_tx::bytes.multicast::cluster [%0], [%1], %2, [%3], %4;"
                 ::"r"(dst), "l"(src), "r"(bytes), "r"(bar), "h"(mask) : "memory");
}
__device__ __forceinline__ void prefetch_l2(const void* p, uint32_t bytes) { asm volatile("cp.async.bulk.prefetch.L2.global [%0], %1;" ::"l"(p), "r"(bytes) : "memory"); }
__device__ __forceinline__ void prefetch_tmap(const CUtensorMap* m) { asm volatile("prefetch.tensormap [%0];" ::"l"(m) : "memory"); }

__device__ __forceinline__ void wg_fence() { asm volatile("wgmma.fence.sync.aligned;" ::: "memory"); }
__device__ __forceinline__ void wg_commit() { asm volatile("wgmma.commit_group.sync.aligned;" ::: "memory"); }
template <int N> __device__ __forceinline__ void wg_wait() { asm volatile("wgmma.wait_group.sync.aligned %0;" ::"n"(N) : "memory"); }
__device__ __forceinline__ uint64_t mkdesc(uint32_t addr, uint32_t lbo, uint32_t sbo, uint32_t mode) {
    return (uint64_t)((addr & 0x3FFFF) >> 4) | ((uint64_t)(lbo >> 4) << 16) | ((uint64_t)(sbo >> 4) << 32) | ((uint64_t)mode << 62);
}

__device__ __forceinline__ void mma16816(float (&c)[4], uint32_t a0, uint32_t a1, uint32_t a2, uint32_t a3, uint32_t b0, uint32_t b1) {
    asm("mma.sync.aligned.m16n8k16.row.col.f32.bf16.bf16.f32 {%0,%1,%2,%3},{%4,%5,%6,%7},{%8,%9},{%0,%1,%2,%3};"
                 : "+f"(c[0]), "+f"(c[1]), "+f"(c[2]), "+f"(c[3]) : "r"(a0), "r"(a1), "r"(a2), "r"(a3), "r"(b0), "r"(b1));
}
__device__ __forceinline__ void mma1688(float (&c)[4], uint32_t a0, uint32_t a1, uint32_t b0) {
    asm("mma.sync.aligned.m16n8k8.row.col.f32.bf16.bf16.f32 {%0,%1,%2,%3},{%4,%5},{%6},{%0,%1,%2,%3};"
                 : "+f"(c[0]), "+f"(c[1]), "+f"(c[2]), "+f"(c[3]) : "r"(a0), "r"(a1), "r"(b0));
}
__device__ __forceinline__ void ldsm_x4(uint32_t& r0, uint32_t& r1, uint32_t& r2, uint32_t& r3, uint32_t a) {
    asm volatile("ldmatrix.sync.aligned.m8n8.x4.shared.b16 {%0,%1,%2,%3}, [%4];" : "=r"(r0), "=r"(r1), "=r"(r2), "=r"(r3) : "r"(a) : "memory");
}
__device__ __forceinline__ void ldsm_x4_t(uint32_t& r0, uint32_t& r1, uint32_t& r2, uint32_t& r3, uint32_t a) {
    asm volatile("ldmatrix.sync.aligned.m8n8.x4.trans.shared.b16 {%0,%1,%2,%3}, [%4];" : "=r"(r0), "=r"(r1), "=r"(r2), "=r"(r3) : "r"(a) : "memory");
}
__device__ __forceinline__ void ldsm_x2(uint32_t& r0, uint32_t& r1, uint32_t a) {
    asm volatile("ldmatrix.sync.aligned.m8n8.x2.shared.b16 {%0,%1}, [%2];" : "=r"(r0), "=r"(r1) : "r"(a) : "memory");
}
__device__ __forceinline__ void ldsm_x2_t(uint32_t& r0, uint32_t& r1, uint32_t a) {
    asm volatile("ldmatrix.sync.aligned.m8n8.x2.trans.shared.b16 {%0,%1}, [%2];" : "=r"(r0), "=r"(r1) : "r"(a) : "memory");
}
__device__ __forceinline__ void stsm_x4(uint32_t a, uint32_t r0, uint32_t r1, uint32_t r2, uint32_t r3) {
    asm volatile("stmatrix.sync.aligned.m8n8.x4.shared.b16 [%0], {%1,%2,%3,%4};" ::"r"(a), "r"(r0), "r"(r1), "r"(r2), "r"(r3) : "memory");
}
__device__ __forceinline__ void stsm_x4_t(uint32_t a, uint32_t r0, uint32_t r1, uint32_t r2, uint32_t r3) {
    asm volatile("stmatrix.sync.aligned.m8n8.x4.trans.shared.b16 [%0], {%1,%2,%3,%4};" ::"r"(a), "r"(r0), "r"(r1), "r"(r2), "r"(r3) : "memory");
}
__device__ __forceinline__ void stsm_x2(uint32_t a, uint32_t r0, uint32_t r1) {
    asm volatile("stmatrix.sync.aligned.m8n8.x2.shared.b16 [%0], {%1,%2};" ::"r"(a), "r"(r0), "r"(r1) : "memory");
}
__device__ __forceinline__ uint32_t movm_t(uint32_t a) {
    uint32_t d;
    asm volatile("movmatrix.sync.aligned.m8n8.trans.b16 %0, %1;" : "=r"(d) : "r"(a));
    return d;
}
__device__ __forceinline__ uint32_t lds32(uint32_t a) { uint32_t v; asm volatile("ld.shared.u32 %0, [%1];" : "=r"(v) : "r"(a) : "memory"); return v; }
__device__ __forceinline__ uint32_t ldsv32(uint32_t a) { uint32_t v; asm volatile("ld.volatile.shared.u32 %0, [%1];" : "=r"(v) : "r"(a) : "memory"); return v; }
__device__ __forceinline__ void sts32(uint32_t a, uint32_t v) { asm volatile("st.shared.u32 [%0], %1;" ::"r"(a), "r"(v) : "memory"); }
__device__ __forceinline__ uint4 lds128(uint32_t a) { uint4 v; asm volatile("ld.shared.v4.u32 {%0,%1,%2,%3}, [%4];" : "=r"(v.x), "=r"(v.y), "=r"(v.z), "=r"(v.w) : "r"(a) : "memory"); return v; }
__device__ __forceinline__ void sts128(uint32_t a, uint4 v) { asm volatile("st.shared.v4.u32 [%0], {%1,%2,%3,%4};" ::"r"(a), "r"(v.x), "r"(v.y), "r"(v.z), "r"(v.w) : "memory"); }

__device__ __forceinline__ void stg128(void* p, uint4 v) { asm volatile("st.global.v4.u32 [%0], {%1,%2,%3,%4};" ::"l"(p), "r"(v.x), "r"(v.y), "r"(v.z), "r"(v.w) : "memory"); }

__device__ __forceinline__ uint4 ldg128(const void* p) { uint4 v; asm volatile("ld.global.v4.u32 {%0,%1,%2,%3}, [%4];" : "=r"(v.x), "=r"(v.y), "=r"(v.z), "=r"(v.w) : "l"(p) : "memory"); return v; }
__device__ __forceinline__ uint2 ldg64(const void* p) { uint2 v; asm volatile("ld.global.v2.u32 {%0,%1}, [%2];" : "=r"(v.x), "=r"(v.y) : "l"(p) : "memory"); return v; }
__device__ __forceinline__ uint32_t ldg32(const void* p) { uint32_t v; asm volatile("ld.global.u32 %0, [%1];" : "=r"(v) : "l"(p) : "memory"); return v; }

__device__ __forceinline__ uint32_t pack2(float lo, float hi) {
    uint32_t r;
    asm("cvt.rn.bf16x2.f32 %0, %1, %2;" : "=r"(r) : "f"(hi), "f"(lo));
    return r;
}
__device__ __forceinline__ float bf_lo(uint32_t v) { return __uint_as_float(v << 16); }
__device__ __forceinline__ float bf_hi(uint32_t v) { return __uint_as_float(v & 0xFFFF0000u); }
__device__ __forceinline__ float rbf(float x) { return __uint_as_float(pack2(0.f, x) & 0xFFFF0000u); }
__device__ __forceinline__ float ex2(float x) { float r; asm("ex2.approx.ftz.f32 %0, %1;" : "=f"(r) : "f"(x)); return r; }

__device__ __forceinline__ float2 ln_finish(float sum, float sumsq) {
    const float m = sum * (1.0f / DM);
    const float v = fmaxf(fmaf(sumsq, 1.0f / DM, -m * m), 0.f);
    float s, r;
    asm("sqrt.approx.ftz.f32 %0, %1;" : "=f"(s) : "f"(rbf(rbf(v) + 1e-5f)));
    asm("rcp.approx.ftz.f32 %0, %1;" : "=f"(r) : "f"(rbf(s)));
    return make_float2(m, r);
}
__device__ __forceinline__ uint32_t ln_finish_packed(float sum, float sumsq) {
    const float m = sum * (1.0f / DM);
    const float v = fmaxf(fmaf(sumsq, 1.0f / DM, -m * m), 0.f);
    float s;
    asm("sqrt.approx.ftz.f32 %0, %1;" : "=f"(s) : "f"(rbf(rbf(v) + 1e-5f)));
    return pack2(s, m);
}
__device__ __forceinline__ float frsq(float x) { float r; asm("rsqrt.approx.ftz.f32 %0, %1;" : "=f"(r) : "f"(x)); return r; }
__device__ __forceinline__ float frcp(float x) { float r; asm("rcp.approx.ftz.f32 %0, %1;" : "=f"(r) : "f"(x)); return r; }
__device__ __forceinline__ bool elect_one() {
    uint32_t p;
    asm volatile("{\n.reg .pred p;\nelect.sync _|p, 0xffffffff;\nselp.u32 %0, 1, 0, p;\n}" : "=r"(p));
    return p != 0;
}
__device__ __forceinline__ void cluster_arrive_relaxed() { asm volatile("barrier.cluster.arrive.relaxed.aligned;" ::: "memory"); }
__device__ __forceinline__ void cluster_wait() { asm volatile("barrier.cluster.wait.aligned;" ::: "memory"); }
__device__ __forceinline__ unsigned long long ld_ll(const unsigned long long* p) {
    unsigned long long v;
    asm volatile("ld.relaxed.gpu.global.b64 %0, [%1];" : "=l"(v) : "l"(p) : "memory");
    return v;
}
__device__ __forceinline__ void st_ll(unsigned long long* p, uint32_t payload, uint32_t tag) {
    const unsigned long long v = (unsigned long long)payload | ((unsigned long long)tag << 32);
    asm volatile("st.relaxed.gpu.global.b64 [%0], %1;" ::"l"(p), "l"(v) : "memory");
}
__device__ __forceinline__ uint4 ld_ll4(const uint4* p) {
    uint4 v;
    asm volatile("{\n.reg .b128 t;\n.reg .b64 a, b;\nld.relaxed.gpu.global.b128 t, [%4];\nmov.b128 {a, b}, t;\nmov.b64 {%0, %1}, a;\nmov.b64 {%2, %3}, b;\n}"
                 : "=r"(v.x), "=r"(v.y), "=r"(v.z), "=r"(v.w) : "l"(p) : "memory");
    return v;
}
__device__ __forceinline__ void st_ll4(uint4* p, uint32_t x, uint32_t y, uint32_t z, uint32_t w) {
    asm volatile("{\n.reg .b128 t;\n.reg .b64 a, b;\nmov.b64 a, {%1, %2};\nmov.b64 b, {%3, %4};\nmov.b128 t, {a, b};\nst.relaxed.gpu.global.b128 [%0], t;\n}"
                 ::"l"(p), "r"(x), "r"(y), "r"(z), "r"(w) : "memory");
}

__device__ __forceinline__ void bulk_s2g(void* dst, uint32_t src, uint32_t bytes) {
    asm volatile("cp.async.bulk.global.shared::cta.bulk_group [%0], [%1], %2;" ::"l"(dst), "r"(src), "r"(bytes) : "memory");
}
__device__ __forceinline__ void bulk_commit() { asm volatile("cp.async.bulk.commit_group;" ::: "memory"); }
__device__ __forceinline__ void bulk_wait() { asm volatile("cp.async.bulk.wait_group 0;" ::: "memory"); }
__device__ __forceinline__ void fence_async_global() { asm volatile("fence.proxy.async.global;" ::: "memory"); }
__device__ __forceinline__ void fence_release() { asm volatile("fence.release.gpu;" ::: "memory"); }
__device__ __forceinline__ void fence_acquire() { asm volatile("fence.acquire.gpu;" ::: "memory"); }
template<int TA, int TB>
__device__ __forceinline__ void wgmma_n192(float (&d)[96], uint64_t da, uint64_t db, int scale_d) {
  asm volatile("{\n.reg .pred p;\nsetp.ne.b32 p, %98, 0;\n"
    "wgmma.mma_async.sync.aligned.m64n192k16.f32.bf16.bf16 "
    "{%0, %1, %2, %3, %4, %5, %6, %7, %8, %9, %10, %11, %12, %13, %14, %15, %16, %17, %18, %19, %20, %21, %22, %23, %24, %25, %26, %27, %28, %29, %30, %31, %32, %33, %34, %35, %36, %37, %38, %39, %40, %41, %42, %43, %44, %45, %46, %47, %48, %49, %50, %51, %52, %53, %54, %55, %56, %57, %58, %59, %60, %61, %62, %63, %64, %65, %66, %67, %68, %69, %70, %71, %72, %73, %74, %75, %76, %77, %78, %79, %80, %81, %82, %83, %84, %85, %86, %87, %88, %89, %90, %91, %92, %93, %94, %95}, %96, %97, p, 1, 1, %99, %100;\n}\n"
    : "+f"(d[0]), "+f"(d[1]), "+f"(d[2]), "+f"(d[3]), "+f"(d[4]), "+f"(d[5]), "+f"(d[6]), "+f"(d[7]), "+f"(d[8]), "+f"(d[9]), "+f"(d[10]), "+f"(d[11]), "+f"(d[12]), "+f"(d[13]), "+f"(d[14]), "+f"(d[15]), "+f"(d[16]), "+f"(d[17]), "+f"(d[18]), "+f"(d[19]), "+f"(d[20]), "+f"(d[21]), "+f"(d[22]), "+f"(d[23]), "+f"(d[24]), "+f"(d[25]), "+f"(d[26]), "+f"(d[27]), "+f"(d[28]), "+f"(d[29]), "+f"(d[30]), "+f"(d[31]), "+f"(d[32]), "+f"(d[33]), "+f"(d[34]), "+f"(d[35]), "+f"(d[36]), "+f"(d[37]), "+f"(d[38]), "+f"(d[39]), "+f"(d[40]), "+f"(d[41]), "+f"(d[42]), "+f"(d[43]), "+f"(d[44]), "+f"(d[45]), "+f"(d[46]), "+f"(d[47]), "+f"(d[48]), "+f"(d[49]), "+f"(d[50]), "+f"(d[51]), "+f"(d[52]), "+f"(d[53]), "+f"(d[54]), "+f"(d[55]), "+f"(d[56]), "+f"(d[57]), "+f"(d[58]), "+f"(d[59]), "+f"(d[60]), "+f"(d[61]), "+f"(d[62]), "+f"(d[63]), "+f"(d[64]), "+f"(d[65]), "+f"(d[66]), "+f"(d[67]), "+f"(d[68]), "+f"(d[69]), "+f"(d[70]), "+f"(d[71]), "+f"(d[72]), "+f"(d[73]), "+f"(d[74]), "+f"(d[75]), "+f"(d[76]), "+f"(d[77]), "+f"(d[78]), "+f"(d[79]), "+f"(d[80]), "+f"(d[81]), "+f"(d[82]), "+f"(d[83]), "+f"(d[84]), "+f"(d[85]), "+f"(d[86]), "+f"(d[87]), "+f"(d[88]), "+f"(d[89]), "+f"(d[90]), "+f"(d[91]), "+f"(d[92]), "+f"(d[93]), "+f"(d[94]), "+f"(d[95])
    : "l"(da), "l"(db), "r"(scale_d), "n"(TA), "n"(TB));
}

template<int TA, int TB>
__device__ __forceinline__ void wgmma_n48(float (&d)[24], uint64_t da, uint64_t db, int scale_d) {
  asm volatile("{\n.reg .pred p;\nsetp.ne.b32 p, %26, 0;\n"
    "wgmma.mma_async.sync.aligned.m64n48k16.f32.bf16.bf16 "
    "{%0, %1, %2, %3, %4, %5, %6, %7, %8, %9, %10, %11, %12, %13, %14, %15, %16, %17, %18, %19, %20, %21, %22, %23}, %24, %25, p, 1, 1, %27, %28;\n}\n"
    : "+f"(d[0]), "+f"(d[1]), "+f"(d[2]), "+f"(d[3]), "+f"(d[4]), "+f"(d[5]), "+f"(d[6]), "+f"(d[7]), "+f"(d[8]), "+f"(d[9]), "+f"(d[10]), "+f"(d[11]), "+f"(d[12]), "+f"(d[13]), "+f"(d[14]), "+f"(d[15]), "+f"(d[16]), "+f"(d[17]), "+f"(d[18]), "+f"(d[19]), "+f"(d[20]), "+f"(d[21]), "+f"(d[22]), "+f"(d[23])
    : "l"(da), "l"(db), "r"(scale_d), "n"(TA), "n"(TB));
}

__device__ __forceinline__ void wgmma_rs80(float (&d)[40], const uint4& a, uint64_t db, int scale_d) {
  asm volatile("{\n.reg .pred p;\nsetp.ne.b32 p, %45, 0;\n"
    "wgmma.mma_async.sync.aligned.m64n80k16.f32.bf16.bf16 {%0,%1,%2,%3,%4,%5,%6,%7,%8,%9,%10,%11,%12,%13,%14,%15,%16,%17,%18,%19,%20,%21,%22,%23,%24,%25,%26,%27,%28,%29,%30,%31,%32,%33,%34,%35,%36,%37,%38,%39}, {%40,%41,%42,%43}, %44, p, 1, 1, 1;\n}\n"
    : "+f"(d[0]), "+f"(d[1]), "+f"(d[2]), "+f"(d[3]), "+f"(d[4]), "+f"(d[5]), "+f"(d[6]), "+f"(d[7]), "+f"(d[8]), "+f"(d[9]), "+f"(d[10]), "+f"(d[11]), "+f"(d[12]), "+f"(d[13]), "+f"(d[14]), "+f"(d[15]), "+f"(d[16]), "+f"(d[17]), "+f"(d[18]), "+f"(d[19]), "+f"(d[20]), "+f"(d[21]), "+f"(d[22]), "+f"(d[23]), "+f"(d[24]), "+f"(d[25]), "+f"(d[26]), "+f"(d[27]), "+f"(d[28]), "+f"(d[29]), "+f"(d[30]), "+f"(d[31]), "+f"(d[32]), "+f"(d[33]), "+f"(d[34]), "+f"(d[35]), "+f"(d[36]), "+f"(d[37]), "+f"(d[38]), "+f"(d[39])
    : "r"(a.x), "r"(a.y), "r"(a.z), "r"(a.w), "l"(db), "r"(scale_d));
}

__device__ const __align__(1024) uint32_t c_fft[11264] = {
0x2ddc2dba,0x2fe62eb5,0x2ed02eb5,0xafffaf6e,0x2e1f2dfe,0x2e3f2fbc,0x2f022ee9,0xad27af30,0x2e5e2e3f,0x1fd92b5e,0x2f302f1a,0x244ea875,0x2e992e7c,0xad96a993,0x2f5a2f46,0x2e992c32,
0xad00ad72,0xa17eac32,0xa17ea515,0xabb79cb6,0xac07ac87,0x2dfe29f1,0x1fd99648,0xafedae99,0xa9f1ab05,0x2fd42fbc,0x26a1244e,0xad96af91,0xa765a8d5,0x2aaa2e3f,0x29932875,0x2515a8d5,
0xae99adfe,0xb000aee9,0xaf6eafbc,0x2c872f30,0xaf80af1a,0xac32af02,0xae7caf02,0xaaaa217e,0xaff4afc9,0x2b5e9cb6,0xad27addc,0xaff4ae7c,0xafedb000,0x2ffc2eb5,0xab05ac5d,0xacd8af5a,
0x2c072d27,0x9fd92bb7,0xadfead00,0x2fed2e1f,0x25db2993,0xaf6eacb0,0xaf6eaed0,0x2c5d2f46,0xa5151648,0xaddcafdd,0xafffafd4,0xac321648,0xabb7a934,0x28d5a814,0xafa0afed,0xaff4af30,
0x2f302e3f,0x2fed2f1a,0x28142b5e,0x2934a875,0x30002fc9,0x26a12ddc,0xa5db1cb6,0x30002e7c,0x2f462fd4,0xaed0aa4e,0xacb0aa4e,0x29932e99,0x2d272e5e,0xae3faffc,0xaf02adfe,0xae1fa814,
0xa9f1acd8,0x26a1ab05,0x2fd42ffc,0xad96afed,0x2515a30e,0x2fff2e1f,0x2ddc2f1a,0x2c32a30e,0x2d272aaa,0x28752e7c,0x28752c32,0x2fa02f80,0x2f912e99,0xaee9a9f1,0xa8141648,0x9fd92c87,
0xafa0ae7c,0xafafaf46,0x2d002993,0xafa0ac32,0xaf91b000,0x244eac5d,0x2fbc2eb5,0xab05af5a,0xac87ae5e,0x30002dfe,0x2f6e2ffc,0x2e992814,0x1cb6a875,0x25152e1f,0x2c322e1f,0x2d722ff4,
0x27652c87,0xa9932a4e,0xaaaaadba,0xa5152c87,0xabb7a44e,0xafa0af30,0x28d59fd9,0xaff4ae5e,0xaf91ae1f,0x2814abb7,0x2ee92d00,0x1fd9ad27,0xaf5aafff,0x2fd42ed0,0x2fd42fe6,0x30002ddc,
0x2f462f6e,0x2c322fdd,0x2e7c2fdd,0xa993b000,0xab5e2934,0xafafacd8,0xad00244e,0x2f1a2dfe,0xaee9afaf,0x2f30a17e,0xadfeaff8,0xafbca30e,0x2c5da765,0xa9f12ddc,0x2d969cb6,0x2c5dacb0,
0x2bb7a993,0x2f1aa515,0x2f1a2765,0xaff4aaaa,0x2e5e2fd4,0xab052dba,0x29342f6e,0x2ee9a6a1,0xadba1fd9,0xa5dbafed,0xafddac07,0xaa4e2dfe,0xacb0aff8,0x2ddc2f02,0x9cb6ae3f,0xa765aff8,
0xaeb5af91,0xaa4eafed,0x9648ae5e,0xac5d2d4d,0x2ddca17e,0x2e7c2e3f,0x2fc92e3f,0x1cb6afa0,0x2bb72fe6,0xaff8a993,0xab5e2aaa,0x2bb72fc9,0xafbcaa4e,0x2f30a5db,0xadfeafdd,0xaee9adba,
0xacd828d5,0xaf91230e,0xaf30af02,0x2c072fa0,0xac5dafff,0x2dbaac32,0x2dbaa515,0xae99addc,0x2fc929f1,0xa9932eb5,0x2aaa2fdd,0x2fe629f1,0xa30e2dfe,0xa17eafed,0xaff8ac07,0xafaf1fd9,
0x2dfe2faf,0x28142ff8,0xae5e217e,0x2ffc230e,0xaf5aa515,0xac87af46,0xa6a1af80,0xaf5a2765,0x1cb6ae99,0x2e7c2dba,0x2fc92dba,0x2ddcac5d,0x2f1a2ee9,0xafafab05,0xad002934,0xab5e2e5e,
0x2dbaa814,0x2fdd9fd9,0x25db2f91,0x2a4eaee9,0x27652faf,0xaf4628d5,0xaf80ae1f,0xa5152faf,0xafa0addc,0x2e3fac32,0x2e3fa515,0xa17eafff,0x2dfea6a1,0xacd82dba,0x244e2f6e,0x29342fd4,
0xad27afc9,0xa30eafff,0x2faf2d72,0xad27ae7c,0x2ffc2a4e,0x28142fdd,0xae5e25db,0x2dfe2dba,0xac5d2c07,0xaa4eaf91,0x9648af30,0xaeb5acd8,0xa993aff4,0x2c322f1a,0x2e7c2f1a,0x2f462bb7,
0xae7c26a1,0xafff1648,0x2d72aa4e,0xafc926a1,0x230eaee9,0x2ff89fd9,0x217e2f91,0x2fafa814,0x2d4d2fa0,0xafed230e,0xae5eaf02,0xaf9128d5,0xb000aaaa,0x2fdda515,0x2fdd2765,0x2f6ea993,
0x9cb63000,0xacb02fd4,0xa7652fd4,0x2ddcaf5a,0x217eaffc,0x2ff4ac07,0x2875afbc,0xaff82934,0xa44e2ff4,0xadfea8d5,0xa9342fa0,0x2cd82bb7,0x25dbafe6,0x16482f46,0x29f1af80,0x25dbafc9,
0x2ff41cb6,0x2e1f2765,0x2e1f2cb0,0xa875addc,0xafbca5db,0x1fd9af5a,0xad4dad96,0xacd82fdd,0x2f5a2934,0xaeb52ee9,0x2c5d2e5e,0x3000ab05,0xaed0ab5e,0x2f80a30e,0xaaaaaf02,0xacb0ab5e,
0x25dbaffc,0x2d96afbc,0x2f5aac07,0xafdd2934,0xaaaa2fa0,0xafc92875,0xafe62875,0x29932d27,0x2d00aed0,0x28d52d72,0x2ff89cb6,0x2d00afe6,0xae5e2d96,0x2d4dafd4,0xaf91a6a1,0xafed29f1,
0xafbca17e,0xad4da875,0x1fd9aff4,0xacd82ff8,0x2e992aaa,0xaa4e2fe6,0xaa4e2fc9,0x2fd4a993,0xacb0ad96,0x2fffac87,0x2d72aeb5,0xa765ad96,0x28752f30,0xab5eac07,0xaf1a2cd8,0xae3f2f91,
0xa9342ff4,0xae5e2fa0,0xaee9a8d5,0x2b052bb7,0x2d96aed0,0x2eb59cb6,0x2c872d72,0x2d96afe6,0xaf802c5d,0x2765af6e,0xa515af6e,0xaf4625db,0x2ff8a44e,0xaff42d4d,0xa8752ffc,0xa17e2ee9,
0x2f5a244e,0x2c5d2934,0xaeb52dfe,0x3000acd8,0xacb0ad00,0x2d72aff8,0x2fffa8d5,0xa765ad00,0x217e2f80,0xaf022515,0xaf02a765,0xaf1a2f46,0x2b05afdd,0xa8142f5a,0x2c072d96,0x2d4d25db,
0x2b5eafe6,0x2f02af80,0x230e2f46,0x2b5eafc9,0xaf302d96,0xacd8a6a1,0x2c07afd4,0xaf9129f1,0x2fdda44e,0xad962ffc,0xaf5a2d4d,0xa5db2ee9,0xad72abb7,0x2e7ca17e,0x2fc9a17e,0x2fffad00,
0xaed0a5db,0xaaaaa9f1,0x2f809648,0xacb0a5db,0x28752e5e,0xaf1a2f91,0xab5ead4d,0xae3f2fed,0x2b05aff8,0x2c072875,0xa8142ff4,0x2d4d217e,0xaf6e2d72,0x2eb5afc9,0x2eb5ae7c,0x2dbaafff,
0xaf802f5a,0xafc92e99,0xafe62e99,0x2f46ad96,0x28d52b05,0xaf022fed,0x230e2cd8,0x2fa0affc,0x2fbcaf02,0xa9342d27,0x2ffcae1f,0x2c07ae3f,0xa6a1ac32,0x2a4e9cb6,0x9648ad72,0xa6a1a515,
0x28752aaa,0xa8d52cb0,0xa8d52ed0,0x2e3faf80,0x2fedaeb5,0x29349648,0x2f30aa4e,0x2814ac5d,0x1648ad4d,0x2e99acd8,0x2c87afbc,0xa9f11fd9,0xafe62d27,0x2fffafaf,0xaddc230e,0xaed02d27,
0x2fd4af30,0x2f6eae5e,0x2dbaa44e,0xa6a19fd9,0x1cb6ad27,0x2fe6aff4,0x2ed0aff4,0xad722b5e,0xafaf2cb0,0x2e1faf46,0xa8d5a993,0xafaf2ed0,0xac072f6e,0x2934ac87,0xaffc2e99,0xafbc3000,
0xa44eab5e,0x2b05ad00,0x2f91afaf,0xafbc2f1a,0xafd42d72,0x1648a765,0x1648acb0,0xafdd2fff,0xac322f5a,0xaaaa26a1,0xaf802c87,0xae7c2f5a,0x2d009fd9,0xae1f2cd8,0xad272fbc,0xabb72d4d,
0xaffc2f02,0xaee92e1f,0x244ead27,0xad4d2e3f,0xa9f12e7c,0xafdd2f80,0xaeb52aaa,0xa9f12c32,0x2d72a5db,0xafe63000,0xaed03000,0x9cb626a1,0x2fa0afbc,0xaf022f91,0x230e2b05,0x28d5a44e,
0x96482c07,0xac872d4d,0xae992b05,0x29f1a814,0x2ed0abb7,0xa9932b5e,0xaf462ff8,0x2cb0abb7,0x2f1aafff,0xa30e2765,0xa30e2cb0,0x2e1fad72,0x1fd9ac5d,0x244e9648,0x2e5eaa4e,0x2f30aeb5,
0x2ff8aed0,0x2e3faddc,0xaf022fff,0x2ff8afe6,0x2d4daf6e,0x2ee9ae99,0xa44e2c87,0x2ffcb000,0xa6a1a814,0x2f6eaf30,0x2dbaa934,0x2fd4afed,0xaf462d00,0x2fc9afa0,0x2fe6afa0,0x2f80afaf,
0x2515ac5d,0x2d72ad96,0x1cb629f1,0x2c32ac5d,0xad002814,0x2d27ad4d,0x2e1fab05,0x2bb7ac07,0xaffc2f1a,0x2cd8ad00,0x2fedafaf,0x2b05ab5e,0xadba2f80,0x2c87acb0,0x2c87aed0,0x2a4eaaaa,
0x2f802f6e,0x2fc92fdd,0x2fe62fdd,0xaf46b000,0x2fa02f91,0x2bb72e5e,0x2ff42fed,0xa8d5ad4d,0x2fbc2faf,0xa934217e,0x2ffc2ff8,0x2c07230e,0x2fd42fc9,0xaf5aad72,0x30002fff,0x2fd42e7c,
0x2bb72aaa,0x2f1a2cb0,0x2f1a2ed0,0xaff4af80,0x2cd82c5d,0x2f303000,0x2f912f5a,0xac07aeb5,0x2dba2d4d,0x25db2cd8,0x2fdd2fbc,0x2a4e9fd9,0x2e7c2e1f,0xad72a875,0x2fff2ff4,0x2fc92e1f,
0xa6a1a934,0x29f1a44e,0x2d962cd8,0xafd4adfe,0x1cb6a17e,0x2fe62e3f,0x2ed02e3f,0xad72afa0,0x28752515,0x2d272f80,0x2fa02f46,0x2875a765,0x2c072a4e,0xa93425db,0x2ffc2fdd,0x2fbc2dba,
0xae5eaf1a,0xa934ae3f,0x2b052875,0xaee9ab5e,0xac5dad72,0x2dba2765,0x2dba2cb0,0xae99afff,0xa765aa4e,0x2f802fd4,0x2f462e99,0x2515aa4e,0x230e9fd9,0x217e2cd8,0x2ff82fbc,0x2faf2d4d,
0xaffcafaf,0xaee9aff8,0x244ea17e,0xad4da30e,0xaf6eafe6,0x25dbaaaa,0x2c5d2993,0xaf6eafc9,0xad72ae99,0x2fe62dba,0x2ed02dba,0x1cb6ac5d,0xa8d5ac07,0x2bb72f30,0x2ff42f91,0x2fa02cd8,
0xadbaac07,0xafddad4d,0xa5dbab05,0xaa4e2814,0xafc9af02,0xaaaaaf1a,0x2993217e,0xafe6af02,0xafa0afff,0x2e3f2765,0x2e3f2cb0,0xa17ead72,0xad4daeb5,0x2e5e3000,0x2fed2f5a,0x2f912c5d,
0xa17e2765,0xad001cb6,0xabb7addc,0xa17e2cb0,0xad4daa4e,0xaee9afdd,0x244ea5db,0xaffcadba,0xafd4aee9,0x29f1a934,0x2d962b05,0xa6a1ae5e,0xaf46aff4,0x2fc92f1a,0x2fe62f1a,0x2f802bb7,
0x2cb02eb5,0x1cb62dba,0xaddcaf6e,0x27652eb5,0xa30e2814,0xaff8ad4d,0xa17eab05,0xafafac07,0xadfeab5e,0xa44eae3f,0x2cd82875,0xa934af1a,0xb000af80,0x2fdd2cb0,0x2fdd2ed0,0x2f6e2aaa,
0x2d723000,0x25152fd4,0x2c322fd4,0x1cb6af5a,0xae1f9fd9,0xae3faee9,0xaf02a814,0x2d272f91,0xacd8aff4,0x2ffc28d5,0xab05afa0,0xafedabb7,0x2e992515,0xad962aaa,0x2f5a2993,0x2e99a765,
0x2ff42ddc,0x2e1f2ed0,0x2e1f2fe6,0xa875afff,0xa8142c87,0xaffca9f1,0xadfe1648,0x2e5e2e99,0xaf5aaf30,0x2eb5a814,0xac5dafed,0xb000a934,0x2c32a8d5,0xa9932e3f,0x2f462875,0x2e7ca8d5,
0x2e991fd9,0x30002814,0x2f6e2ee9,0xac87af91,0x29932fa0,0xaed02875,0xacb02875,0x2f462d27,0xaff4ac32,0x2b5eaddc,0xad27afff,0xaff4a515,0x244ead96,0x1fd92fd4,0x2f3026a1,0x2e5ea9f1,
0x2814ad27,0x2dfeabb7,0x2ffc2d00,0xae5eae1f,0x2e992f80,0xaa4e2e7c,0xaa4e2c32,0x2fd42aaa,0xae7c1648,0x9cb6afdd,0xaddcafd4,0xafc91648,0xa875af91,0x2b5e2fbc,0x2f1a244e,0x2e3fab05,
0xab05aff4,0x244eafa0,0x2fbc28d5,0xaf91abb7,0x30002c32,0x26a12fff,0xa5db2ddc,0x30002515,0xaaaa2c5d,0xac32af6e,0xae7caf6e,0xaf8025db,0xad27afed,0x2e3f2dfe,0x2f021fd9,0x2e1fac07,
0xaf5aae5e,0xac5daf30,0x2eb59fd9,0xb000a44e,0x2e7ca30e,0x2ddc2e1f,0x1cb62f1a,0x2fc9a30e,0x217e2f46,0xaf02acb0,0xaf02aed0,0xaf1a2993,0xaf30ae99,0x2fbc29f1,0x2ee99648,0x2dfeac87,
0xafa0a515,0xafafa993,0x2d00aaaa,0xafa02765,0x2934ad96,0x2fed26a1,0x28142fd4,0x2f30a9f1,0x2c872fed,0xb0009fd9,0xaf6eadfe,0xae992c07,0xafffabb7,0x2fe6a17e,0x2ed0a17e,0x2ddcad00,
0xac322c87,0xaf462a4e,0x2993adba,0xae7c2c87,0xa875afed,0x2f1aab05,0x2b5e2ffc,0x2e3facd8,0x2f302e1f,0xaee92bb7,0xafbcad00,0xadfe2d27,0xaf6e9cb6,0x2eb5ac32,0x2eb5a515,0x2dbaad72,
0xaaaa2f5a,0xaed02e99,0xacb02e99,0x2f80ad96,0x2b5eaf30,0x2fafa44e,0x2d00ae5e,0xaf1a9fd9,0xac072f02,0xab05ad27,0xad4d2e1f,0x28142e3f,0x2c5daed0,0xa9f12fff,0x2d96addc,0x2c5dafe6,
0x28752f80,0xa8d52fe6,0xa8d52fc9,0x2e3faf46,0xa44eafd4,0x2f91adba,0x2b05af6e,0xafbc26a1,0x96482ffc,0xae99a44e,0xac872ee9,0x29f12d4d,0x2515aff8,0x1cb62f02,0x2d72ae3f,0x2c32aff8,
0x2eb52b05,0x2a4e2cd8,0x16482fed,0x2c5daffc,0xad72ad27,0x2cb0aff4,0x2765aff4,0xafff2b5e,0x2bb72e7c,0xaff82aaa,0xab5e2f80,0x2bb72c32,0xa814af6e,0x2b052c87,0x2d4dae99,0x2c07b000,
0x2feda8d5,0x2f30a30e,0x29342f02,0x2814afa0,0xafd49cb6,0x1648aed0,0x1648afe6,0xafdd2d72,0x2ed029f1,0xaf462eb5,0xa9932fdd,0x2cb029f1,0xad00ad4d,0x2e1f244e,0x2d27aee9,0x2bb7affc,
0x2d4daf02,0x2fbcae1f,0x2cd82d27,0x9fd9ae3f,0xaf5a2cb0,0xac87a993,0xa6a1af46,0xaf5a2ed0,0x2fffa5db,0xacb03000,0xa7653000,0x2d7226a1,0xaf1aa814,0x2fafa934,0x2d00af30,0x2b5eafed,
0x1648afbc,0x2c87affc,0x2e992934,0xa9f1ac07,0xac322faf,0xaf8028d5,0xaaaaae1f,0xae7c2faf,0x2f1aad72,0xa30e2ed0,0xa30e2fe6,0x2e1f1cb6,0xaffc26a1,0x2fedadba,0x2cd8af6e,0x2b05afd4,
0xad27ac32,0xa30ead72,0x2faf9cb6,0xad27a515,0x1fd92f6e,0xafbc2e99,0xacd8ac87,0xad4d3000,0x2c5dafbc,0x2a4e2b05,0x16482f91,0x2eb5a44e,0xaf802d00,0x2ed0afa0,0x2cb0afa0,0x2aaaafaf,
0xafe626a1,0xaddc1648,0x2fffaa4e,0xaed026a1,0x2d002c07,0xad272ffc,0xae1fa934,0xabb72fbc,0x1fd9afa0,0x2e5ea30e,0x244e2f02,0x2f30a8d5,0xadba2f46,0x2c87afe6,0x2c87afc9,0x2a4eaf80,
0xafff2d96,0xae7c2c5d,0xafc92c5d,0x2d72a9f1,0xa17e2dfe,0xaff42fbc,0xa8752ee9,0x2ff8af30,0x2fedad00,0xad4d2f1a,0x2f91ab5e,0x2e5eafaf,0x25dbae7c,0x16482993,0x29f1af46,0x25dbac32,
0xae3f2fff,0xaff82fc9,0xaff82e7c,0x2f02ad72,0x2c0725db,0xadfe2f5a,0x9fd92d96,0x2fedafdd,0x2f6eaf91,0xa6a12c07,0x2fd4acd8,0x2dbaaf30,0xa765ab5e,0x2aaaa30e,0x2993af02,0x2515ab5e,
0xa5db2dfe,0xad962ee9,0xaf5a2fbc,0x2fddaf30,0x2f46ab5e,0xa7652bb7,0x25152bb7,0x2f80aff8,0x2d00afc9,0x28d59cb6,0x2ff8addc,0x2d00ae7c,0xacd89648,0x2dfeac5d,0x2934aeb5,0x244eaa4e,
0x2c07217e,0x9fd92875,0xadfe2ff4,0x2fedaff8,0x2fddaf46,0x29f1a515,0x29f12765,0x2eb5af80,0x2515ad96,0x2ddcac87,0x2fffaeb5,0x2c32ad96,0xaf022b05,0x2fa0aee9,0x28d5ae5e,0x230ea934,
0x2f91ad00,0x2cd8ab5e,0xac072f1a,0x2f30afaf,0x2d96afc9,0x2eb5addc,0x2c879cb6,0x2d96ae7c,0xa993a6a1,0x2fc9af5a,0x2fe6af5a,0x2aaaac87,0xaff82e5e,0x2ff4affc,0x2875adfe,0x217ea814,
0x2f6eafed,0x2fd4af91,0xa6a12d4d,0x2dbaae5e,0x2515ad00,0x2fffaff8,0x2ddca8d5,0x2c32ad00,0xae1f2993,0x2fafafe6,0x2fafafc9,0x28d5aaaa,0xaf912fdd,0x2ee9af5a,0x2814ad96,0x1fd9a5db,
0x2b5eae7c,0x2f02af46,0x230e2993,0x2b5eac32,0xab059648,0x2e5eaeb5,0x2ee9ac5d,0x2934aa4e,0xafdd2e5e,0x2d96adfe,0x2f5aaffc,0x25dba814,0xaddc2faf,0x2cb0ad27,0x2765ad27,0x1cb6a30e,
0xa765a5db,0x2993a9f1,0x2aaa9648,0x2515a5db,0xaf022cd8,0x28d5a934,0x2fa0adfe,0x230ea44e,0xaf912ff8,0x2814a875,0x2ee9aff4,0x1fd9a17e,0xaa4e2ddc,0x26a1a765,0x26a1acb0,0x16489cb6,
0x2d722d96,0x25152c5d,0x2c322c5d,0x1cb6a9f1,0x2d272d4d,0xad00a814,0x2bb72c07,0x2e1f2b05,0x2cd82d00,0xaffcaf1a,0x2b052b5e,0x2fed2faf,0x2c872cb0,0xadbaaf80,0x2a4e2aaa,0x2c872ed0,
0x2e3f2ddc,0x2ff82ed0,0x2ff82fe6,0xaf02afff,0x2ee92e99,0x2d4d2f6e,0x2ffc3000,0xa44eac87,0x2f6e2f30,0xa6a12814,0x2fd42fed,0x2dba2934,0x2fc92fa0,0xaf46ad00,0x2f802faf,0x2fe62fa0,
0xac87ad4d,0x9648ac07,0x29f12814,0xae99ab05,0xa993ab5e,0x2ed02bb7,0x2cb02bb7,0xaf46aff8,0xa30ea765,0x2f1a2fff,0x2e1f2d72,0xa30eacb0,0x244e1648,0x1fd92c5d,0x2f302eb5,0x2e5e2a4e,
0xaee9ae1f,0xaffcaf02,0xad4dae3f,0x244e2d27,0xafddaf80,0xa9f1ae7c,0xa9f1ac32,0xaeb5aaaa,0xafe6b000,0x2d7225db,0x9cb6a6a1,0xaed0b000,0xaf02af91,0x2fa02fbc,0x28d5244e,0x230eab05,
0x2b052d00,0xa44e2b5e,0xafbcaf1a,0x2f912faf,0x16482765,0xafd4ad72,0xafddafff,0x16482cb0,0xaaaaa6a1,0xac32af5a,0xae7caf5a,0xaf80ac87,0xae1facd8,0x2d001fd9,0xabb7ad4d,0xad27afbc,
0x2f6e2e5e,0x2fd42f30,0xa6a11fd9,0x2dba244e,0x2fe62ff4,0x1cb62d27,0xad72ab5e,0x2ed02ff4,0x2e1f2f46,0xafafacb0,0xafafaed0,0xa8d52993,0x29342c87,0xac07af6e,0xafbcb000,0xaffcae99,
0xa8d5acb0,0x2875aaaa,0x2e3f2f80,0xa8d5aed0,0x29341648,0x2fed2eb5,0x28142c5d,0x2f302a4e,0x2e992cd8,0x16482d4d,0xa9f19fd9,0x2c872fbc,0x2fff2faf,0xafe6ad27,0xaed0ad27,0xaddca30e,
0xafc9ae99,0xaf80af5a,0x2f462d96,0xafe6ae99,0xaf02afed,0x28d5ab05,0x2fa02ffc,0x230eacd8,0xa934ad27,0x2fbc2f02,0x2c072e3f,0x2ffc2e1f,0x2a4e1cb6,0xa6a12c32,0xa6a12515,0x96482d72,
0xaaaa29f1,0xaed025db,0xacb025db,0x2f801648,0xaf1aaf91,0x2875ae5e,0xae3fafed,0xab5e2d4d,0x2c07a875,0x2b052ff8,0x2d4da17e,0xa814aff4,0x2eb52fc9,0xaf6ead72,0x2dba2fff,0x2eb52e7c,
0x2f022f80,0x2b5e2fe6,0x2b5e2fc9,0x230eaf46,0xacd826a1,0xaf30ad96,0xaf91a9f1,0x2c072fd4,0xad96affc,0x2fdd244e,0xa5dbaee9,0xaf5aad4d,0x2e7c217e,0xad722bb7,0x2fff2d00,0x2fc9217e,
0x2c5da934,0x2f5aa44e,0x30002cd8,0xaeb5adfe,0x2d722ff8,0xacb02d00,0xa7652d00,0x2fff28d5,0xaf02a515,0x217eaf80,0xaf1aaf46,0xaf022765,0xa814af5a,0x2b052fdd,0x2d4da5db,0x2c07ad96,
0xae5eafa0,0xa934aff4,0x2b05abb7,0xaee928d5,0x2eb51cb6,0x2d962ed0,0x2d962fe6,0x2c87ad72,0x27652f6e,0xaf80ac5d,0xaf46a5db,0xa5152f6e,0xaff4ad4d,0x2ff8244e,0xa17eaee9,0xa875affc,
0xad4d2875,0xafbc217e,0xacd8aff8,0x1fd92ff4,0xaa4eafe6,0x2e99aaaa,0x2fd42993,0xaa4eafc9,0x2fff2c87,0xacb02d96,0xa7652d96,0x2d722eb5,0xab5e2c07,0x2875af30,0xae3faf91,0xaf1aacd8,
0x2d962fbc,0x25db2ffc,0xafdda934,0x2f5a2c07,0xafc9a875,0xaaaaafa0,0x2993ad27,0xafe6a875,0x28d5ad72,0x2d002ed0,0x2d002fe6,0x2ff81cb6,0x2d4d2fd4,0xae5ead96,0xafeda9f1,0xaf9126a1,
0x2e1fa765,0x2ff49cb6,0xa8752ddc,0x2e1facb0,0x1fd92f5a,0xafbc25db,0xacd8afdd,0xad4d2d96,0xaeb5aee9,0x2f5aa934,0x30002b05,0x2c5dae5e,0x2f80230e,0xaed02b5e,0xacb02b5e,0xaaaa2f02,
0xacb0afd4,0x9cb6b000,0x2ddc2f5a,0xa765afd4,0x2ff42c07,0x217e2ffc,0xaff8a934,0x28752fbc,0xadfe28d5,0xa44eaff4,0x2cd8abb7,0xa934afa0,0x1648af46,0x25db2fe6,0x25db2fc9,0x29f12f80,
0xafff9648,0xae7ca6a1,0xafc9a6a1,0x2d722a4e,0x2ff81fd9,0x230e2ee9,0x2faf2814,0x217eaf91,0xafeda30e,0x2d4dafa0,0xaf91a8d5,0xae5e2f02,0x2fdd2515,0xb0002aaa,0x2f6e2993,0x2fdda765,
0xa30e2fff,0xad272fc9,0xad272e7c,0x2fafad72,0x2814afdd,0x2ffcaa4e,0x2dfeadba,0xae5ea5db,0xaa4e2f91,0xac5dac07,0xaeb52cd8,0x96482f30,0x2c32af1a,0xa9932ff4,0x2f46abb7,0x2e7caf1a,
0x2fdd1fd9,0x2dba2814,0x2a4e2ee9,0x25dbaf91,0xaf46a8d5,0x2765afaf,0xa515afaf,0xaf802e1f,0x2e3f2c32,0xafa02ddc,0xa17e2fff,0x2e3f2515,0xacd8adba,0x2dfe26a1,0x2934afd4,0x244eaf6e,
0x2814aff8,0x2dfeafaf,0x2ffca30e,0xae5ea17e,0xac872f46,0xaf5a2515,0xaf5aa765,0xa6a12f80,0x2e7cadba,0x1cb62e99,0x2ddc2c5d,0x2fc9adba,0xafaf2b05,0x2f1aaee9,0xab5eae5e,0xad00a934,
0xaf91a30e,0xacd8a8d5,0x2c07afa0,0xaf302f02,0x2dba2c32,0xac5d2fff,0xae992ddc,0x2dba2515,0xa993aeb5,0x2fc9a9f1,0x2fe6a9f1,0x2aaaafdd,0xa17e2fed,0xa30eadfe,0xafaf9fd9,0xaff82c07,
0xaa4e2fed,0xaeb52f91,0xac5dad4d,0x96482e5e,0x2e7cae3f,0x2ddc217e,0x1cb62fa0,0x2fc9ae3f,0xaff82993,0x2bb7afe6,0x2bb7afc9,0xab5eaaaa,0x2f3025db,0xafbc2a4e,0xaee92dba,0xadfe2fdd,
0x2f1a2515,0x2bb72993,0xaff42aaa,0x2f1aa765,0xab05adba,0x2e5eafd4,0x2ee926a1,0x2934af6e,0xa5db2fed,0xadba9fd9,0xaa4eadfe,0xafdd2c07,0x2ddcaf02,0xacb02ff8,0xa7652ff8,0x9cb62e3f,
0x2c32afdd,0x2f46af6e,0xa9933000,0x2e7cafdd,0xafaf2cd8,0xab5ea934,0x2f1aadfe,0xad00a44e,0x2f30217e,0xaee92faf,0xafbc230e,0xadfe2ff8,0xa9f1addc,0x2c5d2765,0x2c5d2cb0,0x2d961cb6,
0xa993aa4e,0x2765ac87,0xa515ac87,0xaaaa2dba,0xafa02f30,0xabb7244e,0xaff42e5e,0x28d51fd9,0x28142bb7,0xaf912e1f,0x1fd92d27,0x2ee9ad00,0x2fd4aed0,0xaf5a2fff,0x3000addc,0x2fd4afe6,
0xafaf2f46,0xafa02e7c,0xafa02c32,0x2d00a993,0x244e2c5d,0xaf913000,0xab052f5a,0x2fbcaeb5,0x3000adfe,0xac872e5e,0x2e99a814,0x2f6eaffc,0x2515ae1f,0x1cb62875,0x2d72aff4,0x2c32ae1f,
0x26a12b05,0xa9f12cd8,0xad962fed,0x2fd4affc,0x2fffae1f,0x2515230e,0x2c32230e,0x2ddcaf1a,0x2875ae7c,0x2d27aaaa,0x2fa0af80,0x2875ac32,0xaee929f1,0x2f91ae99,0x9fd9ac87,0xa8149648,
0x2fedaf1a,0x2f30ae3f,0x29342875,0x2814ab5e,0x26a1addc,0x3000afc9,0x3000ae7c,0xa5db9cb6,0xaed02a4e,0x2f46afd4,0x2993ae99,0xacb02a4e,0xae3f2ffc,0x2d27ae5e,0xae1f2814,0xaf022dfe,
0x9fd9abb7,0x2c07ad27,0x2fedae1f,0xadfe2d00,0xaf6e2cb0,0x25dba993,0x2c5daf46,0xaf6e2ed0,0xaddc2fdd,0xa5159648,0xac329648,0xafff2fd4,0x28d52814,0xabb72934,0xaff42f30,0xafa02fed,
0xb0002ee9,0xae992dfe,0x2c87af30,0xaf6e2fbc,0xac322f02,0xaf802f1a,0xaaaaa17e,0xae7c2f02,0x2b5e1cb6,0xaff42fc9,0xaff42e7c,0xad272ddc,0x2ffcaeb5,0xafed3000,0xacd82f5a,0xab052c5d,
0xa17e2c32,0xad002d72,0xabb71cb6,0xa17e2515,0x2dfea9f1,0xac072c87,0xafed2e99,0x1fd91648,0x2fd4afbc,0xa9f12b05,0xad962f91,0x26a1a44e,0x2aaaae3f,0xa76528d5,0x251528d5,0x2993a875,
0x2fe6aeb5,0x2ddcadba,0xafff2f6e,0x2ed0aeb5,0x2e3fafbc,0x2e1fadfe,0xad272f30,0x2f02aee9,0x1fd9ab5e,0x2e5eae3f,0x244e2875,0x2f30af1a,0xad962993,0x2e99ae7c,0x2e99ac32,0x2f5aaf46,
0x299329f1,0xa76525db,0x251525db,0x2aaa1648,0x28d52934,0xaf02acd8,0x230e244e,0x2fa02dfe,0x28142875,0xaf91aff8,0x1fd9217e,0x2ee92ff4,0x26a12765,0xaa4eaddc,0x16481cb6,0x26a12cb0,
0x2f022f46,0x2b5e2e7c,0x2b5e2c32,0x230ea993,0x2e5e2eb5,0xab051648,0x29342a4e,0x2ee92c5d,0x2d962dfe,0xafddae5e,0x25db2814,0x2f5a2ffc,0x2cb02d27,0xaddcafaf,0x1cb6230e,0x27652d27,
0x2fd42f91,0x2f6e2fed,0x2dba2e5e,0xa6a1ad4d,0x2fff2ff8,0x25152d00,0x2c322d00,0x2ddc28d5,0x2faf2fe6,0xae1fa993,0x28d52aaa,0x2faf2fc9,0x2ee92f5a,0xaf91afdd,0x1fd925db,0x28142d96,
0x2cd82b5e,0x2f912d00,0x2f302faf,0xac07af1a,0x2eb52ddc,0x2d962fc9,0x2d962e7c,0x2c871cb6,0x2fc92f5a,0xa99326a1,0x2aaa2c87,0x2fe62f5a,0x2ff42ffc,0xaff8ae5e,0x217e2814,0x28752dfe,
0x9fd9a875,0x2c07a17e,0x2fed2ff8,0xadfeaff4,0x29f12515,0x2fdd2f46,0x2eb52f80,0x29f1a765,0x2ddc2c87,0x25152d96,0x2c322d96,0x2fff2eb5,0x2fa02ee9,0xaf02ab05,0x230e2934,0x28d52e5e,
0xad96aee9,0xa5dbadfe,0x2fdd2f30,0xaf5aafbc,0xa765abb7,0x2f462b5e,0x2f802ff8,0x2515abb7,0x28d51cb6,0x2d002fc9,0x2d002e7c,0x2ff82ddc,0x2dfe2c5d,0xacd81648,0x244e2a4e,0x29342eb5,
0xaff8afc9,0xae3fafff,0x2f022d72,0xaff8ae7c,0xadfeaf5a,0x2c07a5db,0x2fed2fdd,0x9fd9ad96,0xa6a1ac07,0x2f6e2f91,0x2dba2f30,0x2fd42cd8,0x2aaa230e,0xa7652b5e,0x25152b5e,0x29932f02,
0xae7cac5d,0xafffad96,0x2d7229f1,0xafc9ac5d,0xaff4afbc,0xa17eadfe,0x2ff82f30,0xa875aee9,0xad4daf1a,0x2fed2d00,0x2e5e2faf,0x2f912b5e,0x1648a993,0x25db2e7c,0x25db2c32,0x29f12f46,
0xaddc9648,0xafe6a6a1,0xaed0a6a1,0x2fff2a4e,0xad27affc,0x2d00ac07,0xabb7afbc,0xae1f2934,0x2e5e230e,0x1fd92fa0,0x2f3028d5,0x244eaf02,0x2c872fe6,0xadbaaf46,0x2a4e2f80,0x2c872fc9,
0xa30e2d72,0xad272c32,0xad272515,0x2faf1cb6,0xafbcae99,0x1fd9af6e,0xad4db000,0xacd82c87,0x2a4eab05,0x2c5d2fbc,0x2eb5244e,0x1648af91,0x2ed02fa0,0xaf80ad00,0x2aaa2faf,0x2cb02fa0,
0x2c872ffc,0x16482fbc,0xa9f12c07,0x2e99a934,0xaf80a8d5,0xac32afaf,0xae7cafaf,0xaaaa2e1f,0xa30eaed0,0x2f1a2d72,0x2e1f9cb6,0xa30eafe6,0x2fed2dba,0xaffca6a1,0x2b052fd4,0x2cd82f6e,
0x2fbc2e1f,0x2d4d2f02,0x9fd92e3f,0x2cd8ad27,0xac872993,0xaf5aacb0,0xaf5aaed0,0xa6a12f46,0xacb0b000,0x2fff25db,0x2d72a6a1,0xa765b000,0x2faf2934,0xaf1a2814,0x2b5e2fed,0x2d002f30,
0x2f30230e,0x2fed28d5,0x28142fa0,0x2934af02,0x16482ed0,0xafd41cb6,0xafddad72,0x16482fe6,0xaf46aeb5,0x2ed0a9f1,0x2cb0a9f1,0xa993afdd,0x2e1fa44e,0xad002d4d,0x2bb72ffc,0x2d272ee9,
0x2a4eacd8,0x2eb5ab05,0x2c5d2ffc,0x1648afed,0x2cb02ff4,0xad722d27,0xafffab5e,0x27652ff4,0xaff8aaaa,0x2bb7ae7c,0x2bb7ac32,0xab5eaf80,0x2b05ac87,0xa8142f6e,0x2c073000,0x2d4d2e99,
0xa8d5afe6,0x2875af80,0x2e3f2f46,0xa8d5afc9,0x2f912dba,0xa44e2fd4,0xafbca6a1,0x2b052f6e,0xae99244e,0x9648affc,0x29f1ad4d,0xac87aee9,0x1cb6af02,0x25152ff8,0x2c322ff8,0x2d722e3f,
0xaed0ae99,0xaaaaaf5a,0x2f802d96,0xacb0ae99,0x2faf244e,0x2b5e2f30,0xaf1a1fd9,0x2d002e5e,0xab052d27,0xac07af02,0x2814ae3f,0xad4dae1f,0xa9f1afff,0x2c5d2ed0,0x2c5d2fe6,0x2d962ddc,
0xaf46aa4e,0xac32ac87,0xae7cac87,0x29932dba,0x2f1a2b05,0xa8752fed,0x2e3f2cd8,0x2b5eaffc,0xaee9abb7,0x2f30ae1f,0xadfead27,0xafbc2d00,0x2eb52c32,0xaf6e1cb6,0x2dba2d72,0x2eb52515,
0xafaf2993,0xafa02515,0xafa0a765,0x2d002aaa,0x2feda6a1,0x29342d96,0x2f3029f1,0x2814afd4,0xb0001fd9,0x2c87afed,0xae99ac07,0xaf6e2dfe,0x2fe6217e,0xafff2bb7,0x2ddc2d00,0x2ed0217e,
0xac5d2f30,0xaf5a2e5e,0xb000244e,0x2eb51fd9,0x2ddcae1f,0x2e7c230e,0x2fc9230e,0x1cb6af1a,0xaf022cb0,0x217eaf46,0xaf1aa993,0xaf022ed0,0x2fbca9f1,0xaf302e99,0x2dfe2c87,0x2ee91648,
0x244e2fa0,0xab052ff4,0xaf912bb7,0x2fbca8d5,0x26a1afff,0x3000ac32,0x3000a515,0xa5dbaddc,0xac322f6e,0xaaaaac5d,0xaf80a5db,0xae7c2f6e,0x2e3fadfe,0xad272fed,0x2e1f2c07,0x2f029fd9,
0x2dfe2bb7,0x28142d27,0xae5e2e1f,0x2ffcad00,0xaa4eae7c,0x2e99af80,0x2fd4aaaa,0xaa4eac32,0x9cb62fdd,0xae7c9648,0xafc99648,0xaddc2fd4,0x2b5eafbc,0xa8752f91,0x2e3f2b05,0x2f1aa44e,
0x3000a814,0x2e999fd9,0xac872f91,0x2f6eaee9,0xaed0a875,0x2993afa0,0x2f46ad27,0xacb0a875,0x2b5e2ddc,0xaff42c32,0xaff42515,0xad272fff,0x1fd9afd4,0x244e2d96,0x2e5e29f1,0x2f30a6a1,
0x2e1faed0,0x2ff4addc,0xa8752fff,0x2e1fafe6,0xaffc29f1,0xa814ac87,0x2e5eae99,0xadfe9648,0x2eb52814,0xaf5a2f30,0xb0002934,0xac5d2fed,0xa993ae3f,0x2c3228d5,0x2e7c28d5,0x2f46a875,
0x2515afd4,0x2d72b000,0x1cb62f5a,0x2c32afd4,0xae3f2ee9,0xae1f1fd9,0x2d27af91,0xaf022814,0x2ffca8d5,0xacd82ff4,0xafed2bb7,0xab052fa0,0xad96aaaa,0x2e99a515,0x2e992765,0x2f5aa993,
0x1cb6adba,0x2cb0aeb5,0x2765aeb5,0xaddc2f6e,0xaff82d4d,0xa30ea814,0xafaf2c07,0xa17e2b05,0xa44e2e3f,0xadfe2b5e,0xa9342f1a,0x2cd8a875,0x2fddacb0,0xb0002f80,0x2f6eaaaa,0x2fddaed0,
0xad009cb6,0xa17ea765,0xa17eacb0,0xabb72ddc,0xaee92fdd,0xad4d2a4e,0xaffc2dba,0x244e25db,0x29f12934,0xafd42ee9,0xa6a12e5e,0x2d96ab05,0x2fc9af1a,0xaf462ff4,0x2f80abb7,0x2fe6af1a,
0xafdd2d4d,0xadba2c07,0xaa4ea814,0xa5db2b05,0xaaaa2f1a,0xafc92f02,0xafe62f02,0x2993a17e,0x2e3fa765,0xafa02fff,0xa17e2d72,0x2e3facb0,0x2e5eb000,0xad4d2eb5,0x2f91ac5d,0x2fedaf5a,
0xaee92ff8,0xaffc2faf,0xad4d230e,0x244e217e,0x25db2aaa,0xaf6e2fe6,0xaf6e2fc9,0x2c5da993,0x2fe6adba,0xad722e99,0x1cb62c5d,0x2ed0adba,0x2bb7af30,0xa8d52c07,0x2fa0acd8,0x2ff4af91,
0xa9342e3f,0xae5e2f1a,0xaee92b5e,0x2b05a875,0x2dbaa765,0xac5d2d72,0xae992fff,0x2dbaacb0,0x2f80afd4,0xa7652a4e,0x25152a4e,0x2f46ae99,0x217eacd8,0x230e1fd9,0x2fafad4d,0x2ff8afbc,
0x29f1244e,0xa6a12934,0xafd42dfe,0x2d96acd8,0x2fe6ae3f,0x1cb6217e,0xad722fa0,0x2ed0ae3f,0x2d27af80,0x2875a515,0x28752765,0x2fa0af46,0xa934a5db,0x2c07aa4e,0x2fbcadba,0x2ffcafdd,
0x2f1aacb0,0x2bb7aaaa,0xaff42f80,0x2f1aaed0,0x2f30b000,0x2cd8ac5d,0xac072eb5,0x2f91af5a,0x25dbacd8,0x2dbaad4d,0x2a4e1fd9,0x2fddafbc,0xad722875,0x2e7cae1f,0x2fc9ae1f,0x2fffaff4,
0x2fc9afdd,0x2f80af6e,0xaf463000,0x2fe6afdd,0x2bb7ae5e,0x2fa0af91,0xa8d52d4d,0x2ff4afed,0xa934a17e,0x2fbcafaf,0x2c07a30e,0x2ffcaff8,0xaf5a2d72,0x2fd4afc9,0x2fd4ae7c,0x3000afff,
0x9d4d9e16,0xada6ae7d,0x9b769c84,0xabf0accf,0x985299e4,0xa897aa43,0x90b6957f,0xa102a5d8,0x13db0a48,0x242c1aad,0x191b1712,0x296d2783,0x1c201aad,0x2c632b1a,0x1db21ce9,0x2e112d3a,
0xa3f4a491,0xae51af42,0xa199a2c6,0xac70ad60,0x9e7ba06b,0xa922ab00,0x97129c20,0xa199a688,0x19e410b6,0x24aa1b76,0x1fa81d4d,0x2a112833,0x222f2102,0x2ce82bf0,0x2445235d,0x2ec92dd8,
0xa6a1a79c,0xaefcb004,0xa4aaa5a5,0xace8adf2,0xa166a35d,0xa9acabbe,0x99e49edf,0xa22fa738,0x1ce913db,0x25281c20,0x2262206b,0x2ab528a4,0x2528242c,0x2d6d2c63,0x271f2623,0x2f822e77,
0xa8a4a954,0xafa8b067,0xa688a7e8,0xad60ae84,0xa38fa528,0xaa37ac3d,0x9c20a0d0,0xa2c6a7e8,0x1edf157f,0x25a51c84,0x2478222f,0x2b592915,0x273825d8,0x2df22ccf,0x28fc284c,0x301d2f16,
0xa9f8aadb,0xb02ab0ca,0xa833a915,0xadd8af16,0xa4dca6a1,0xaac1ac9c,0x9d4da22f,0xa35da84c,0x206b1712,0x26231ce9,0x25bf23f4,0x2bfd2987,0x28a42783,0x2e772d3a,0x2a692987,0x307a2fb5,
0xab4cac31,0xb081b12e,0xa922aa37,0xae51afa8,0xa5f1a80d,0xab4cacfb,0x9e7ba38f,0xa3f4a8a4,0x21661852,0x26a11d4d,0x270524dc,0x2c5029f8,0x29ac2897,0x2efc2da6,0x2bd72ac1,0x30d7302a,
0xac50acf5,0xb0d7b192,0xaa11ab59,0xaec9b01d,0xa705a8ca,0xabd7ad5a,0x9fa8a478,0xa445a8fc,0x2262191b,0x271f1db2,0x282625bf,0x2ca22a69,0x2ab5296d,0x2f822e11,0x2ca22bfd,0x3135307a,
0xacfbadb9,0xb12eb1f7,0xab00ac3d,0xaf42b067,0xa80da987,0xac31adb9,0xa06ba528,0xa491a954,0x235d19e4,0x279c1e16,0x28ca26a1,0x2cf52adb,0x2bbe2a43,0x30042e7d,0x2d5a2c9c,0x319230ca,
0xb185b25c,0xb426b4cc,0xafbbb0b1,0xb1c6b306,0xac76ae18,0xaea3b08a,0xa4dca9ac,0xa738ac37,0x280d1e7b,0x2a0520d0,0x2d472b4c,0x2fdb2d6d,0x30472ee9,0x32663128,0x31f0311b,0x347933a8,
0xb1ddb2c1,0xb453b501,0xb01ab0fb,0xb204b352,0xacbcae77,0xaee9b0ba,0xa528aa05,0xa783ac63,0x284c1edf,0x2a432102,0x2d992bbe,0x30172da6,0x308a2f55,0x32aa315f,0x324f316b,0x34aa33fc,
0xb235b327,0xb481b537,0xb057b145,0xb242b39e,0xad01aed6,0xaf2fb0eb,0xa573aa5d,0xa7cfac90,0x288b1f44,0x2a822134,0x2deb2c18,0x30412ddf,0x30ce2fc2,0x32ef3196,0x32ae31bc,0x34db3428,
0xb28db38e,0xb4afb56d,0xb094b18f,0xb280b3eb,0xad47af36,0xaf75b11b,0xa5bfaab5,0xa80dacbc,0x28ca1fa8,0x2ac12166,0x2e3e2c50,0x306a2e18,0x31113017,0x333531cd,0x330d320e,0x350d3452,
0xb2e5b3f5,0xb4ddb5a3,0xb0d1b1da,0xb2beb41c,0xad8caf95,0xafbbb14b,0xa60aab0d,0xa833ace8,0x29092006,0x2b002199,0x2e902c89,0x30942e51,0x3155304d,0x337a3204,0x336d325f,0x3540347c,
0xb33eb42e,0xb50cb5da,0xb10eb224,0xb2fcb443,0xadd2aff5,0xb001b17c,0xa655ab65,0xa859ad14,0x29482039,0x2b4021cb,0x2ee32cc2,0x30be2e8a,0x31993084,0x33c0323b,0x33cd32b1,0x357234a6,
0xb398b463,0xb53ab612,0xb14bb26f,0xb33bb469,0xae18b02a,0xb024b1ac,0xa6a1abbe,0xa87ead40,0x2987206b,0x2b7f21fd,0x2f362cfb,0x30e72ec3,0x31dd30ba,0x34033273,0x34173303,0x35a534d1,
0xb3f2b497,0xb569b64a,0xb189b2bb,0xb37ab490,0xae5eb05a,0xb047b1dd,0xa6ecac0b,0xa8a4ad6d,0x29c6209d,0x2bbe222f,0x2f882d34,0x31112efc,0x322130f1,0x342632aa,0x34483356,0x35d934fc,
0xb599b682,0xb722b82e,0xb3b9b4b7,0xb4ddb5f9,0xb06ab20e,0xb185b398,0xa8caad99,0xa9f8aefc,0x2bfd2262,0x2cfb23f4,0x313b2f36,0x328d3081,0x344932e2,0x35693453,0x360d3527,0x37bd368b,
0xb5c9b6bb,0xb755b84d,0xb3f8b4df,0xb4feb622,0xb08db23e,0xb1a9b3ca,0xa8f0adc5,0xaa1eaf29,0x2c1e2294,0x2d1b2413,0x31652f6f,0x32b7309d,0x346d331a,0x358e3470,0x36413553,0x37f536ba,
0xb5f9b6f5,0xb789b86d,0xb41cb506,0xb51fb64c,0xb0b1b26f,0xb1cdb3fc,0xa915adf2,0xaa43af55,0x2c3d22c6,0x2d3a242c,0x318f2fa8,0x32e230ba,0x34903352,0x35b3348d,0x3676357e,0x381736e8,
0xb629b72f,0xb7bdb88d,0xb43cb52e,0xb540b676,0xb0d4b2a1,0xb1f0b417,0xa93bae1e,0xaa69af82,0x2c5d22f9,0x2d5a2445,0x31b92fe2,0x330d30d7,0x34b4338b,0x35d934aa,0x36ab35ab,0x38343717,
0xb65ab76a,0xb7f1b8ad,0xb45cb556,0xb561b6a0,0xb0f7b2d2,0xb214b430,0xa961ae4b,0xaa8fafaf,0x2c7d232b,0x2d79245f,0x31e3300e,0x333830f4,0x34d833c3,0x35fe34c7,0x36e035d7,0x38513746,
0xb68bb7a5,0xb813b8ce,0xb47cb57e,0xb582b6ca,0xb11bb303,0xb238b449,0xa987ae77,0xaab5afdb,0x2c9c235d,0x2d992478,0x320e302a,0x33633111,0x34fc33fc,0x362434e4,0x37173604,0x386f3775,
0xb6bdb7e2,0xb82eb8f0,0xb49cb5a7,0xb5a3b6f5,0xb13eb335,0xb25cb463,0xa9acaea3,0xaadbb004,0x2cbc238f,0x2db92491,0x32383047,0x338e312e,0x3520341a,0x364a3501,0x374d3631,0x388d37a5,
0xb6efb80f,0xb849b911,0xb4bdb5d0,0xb5c5b720,0xb162b366,0xb280b47c,0xa9d2aed0,0xab00b01a,0x2cdb23c2,0x2dd824aa,0x32623064,0x33b9314b,0x35453437,0x3670351f,0x3785365e,0x38ab37d6,
0xb865b934,0xb94dba5c,0xb5e7b74c,0xb6fcb85a,0xb2a4b495,0xb3c6b564,0xab26b031,0xac2bb0e4,0x2df824c3,0x2ef6258c,0x33e43168,0x34a13252,0x3697353c,0x37d4362d,0x38ca3803,0x39d038d0,
0xb880b957,0xb96bba84,0xb609b777,0xb720b872,0xb2c8b4af,0xb3ebb57e,0xab4cb047,0xac3db0fb,0x2e1824dc,0x2f1625a5,0x34083185,0x34b7326f,0x36bd355a,0x37fd364c,0x38e9381c,0x39f338eb,
0xb89cb97a,0xb98abaad,0xb62bb7a4,0xb744b88a,0xb2ecb4c9,0xb408b599,0xab72b05d,0xac50b111,0x2e3724f5,0x2f3625bf,0x341e31a2,0x34ce328d,0x36e43577,0x3813366b,0x39093835,0x3a173906,
0xb8b9b99e,0xb9aabad7,0xb64db7d0,0xb768b8a2,0xb310b4e2,0xb41ab5b3,0xab98b074,0xac63b128,0x2e57250f,0x2f5525d8,0x343331c0,0x34e432aa,0x370b3595,0x3828368a,0x3929384e,0x3a3b3922,
0xb8d6b9c3,0xb9cabb02,0xb670b7fd,0xb78cb8ba,0xb335b4fc,0xb42db5ce,0xabbeb08a,0xac76b13e,0x2e772528,0x2f7525f1,0x344931dd,0x34fa32c8,0x373335b3,0x383d36a9,0x39493868,0x3a60393e,
0xb8f3b9e8,0xb9ebbb2d,0xb693b815,0xb7b1b8d2,0xb359b516,0xb43fb5e9,0xabe3b0a1,0xac89b155,0x2e972541,0x2f95260a,0x345f31fa,0x351132e5,0x375b35d2,0x385236c8,0x396a3881,0x3a86395a,
0xb910ba0e,0xba0cbb59,0xb6b6b82c,0xb7d6b8eb,0xb37db530,0xb452b604,0xac05b0b7,0xac9cb16b,0x2eb6255a,0x2fb52623,0x34753217,0x35273303,0x378335f0,0x386836e8,0x398c389b,0x3aac3977,
0xb92eba35,0xba2dbb87,0xb6d9b843,0xb7fbb904,0xb3a2b54a,0xb464b61e,0xac18b0ce,0xacafb182,0x2ed62573,0x2fd5263c,0x348b3235,0x353e3321,0x37ab360e,0x387d3708,0x39ae38b6,0x3ad33994,
0x9ce99db2,0xad3aae11,0x9aad9c20,0xab1aac63,0x9712991b,0xa783a96d,0x8a4893db,0x9aada42c,0x157f10b6,0x25d82102,0x19e41852,0x2a432897,0x1c841b76,0x2ccf2bf0,0x1e161d4d,0x2e7d2da6,
0xa35da445,0xadd8aec9,0xa102a22f,0xabf0ace8,0x9d4d9fa8,0xa833aa11,0x90b699e4,0x9b76a4aa,0x1c201712,0x26882199,0x206b1e7b,0x2b002922,0x22c62199,0x2d602c70,0x249123f4,0x2f422e51,
0xa623a71f,0xae77af82,0xa42ca528,0xac63ad6d,0xa06ba262,0xa8a4aab5,0x93db9ce9,0x9c20a528,0x1edf19e4,0x2738222f,0x235d2166,0x2bbe29ac,0x25a524aa,0x2df22ce8,0x279c26a1,0x30042efc,
0xa84ca8fc,0xaf16b01d,0xa5d8a738,0xaccfadf2,0xa22fa478,0xa915ab59,0x957f9edf,0x9c84a5a5,0x20d01c20,0x27e822c6,0x2528238f,0x2c3d2a37,0x27e82688,0x2e842d60,0x295428a4,0x30672fa8,
0xa987aa69,0xafb5b07a,0xa783a8a4,0xad3aae77,0xa3f4a5bf,0xa987abfd,0x9712a06b,0x9ce9a623,0x222f1d4d,0x284c235d,0x26a124dc,0x2c9c2ac1,0x29152833,0x2f162dd8,0x2adb29f8,0x30ca302a,
0xaac1abd7,0xb02ab0d7,0xa897a9ac,0xada6aefc,0xa4dca705,0xa9f8ac50,0x9852a166,0x9d4da6a1,0x238f1e7b,0x28a423f4,0x280d25f1,0x2cfb2b4c,0x2a372922,0x2fa82e51,0x2c312b4c,0x312e3081,
0xabfdaca2,0xb07ab135,0xa96daab5,0xae11af82,0xa5bfa826,0xaa69aca2,0x991ba262,0x9db2a71f,0x24781fa8,0x28fc2445,0x28ca2705,0x2d5a2bd7,0x2b592a11,0x301d2ec9,0x2cf52c50,0x319230d7,
0xac9cad5a,0xb0cab192,0xaa43abbe,0xae7db004,0xa6a1a8ca,0xaadbacf5,0x99e4a35d,0x9e16a79c,0x2528206b,0x29542491,0x2987280d,0x2db92c31,0x2c3d2b00,0x30672f42,0x2db92cfb,0x31f7312e,
0xb11bb1f0,0xb3a8b479,0xaee9b047,0xb128b266,0xab4cad47,0xad6dafdb,0x9e7ba80d,0xa0d0aa05,0x29ac24dc,0x2c372738,0x2e182c76,0x308a2ea3,0x30b12fbb,0x330631c6,0x325c3185,0x34cc3426,
0xb16bb24f,0xb3fcb4aa,0xaf55b08a,0xb15fb2aa,0xabbead99,0xada6b017,0x9edfa84c,0xa102aa43,0x2a052528,0x2c632783,0x2e772cbc,0x30ba2ee9,0x30fb301a,0x33523204,0x32c131dd,0x35013453,
0xb1bcb2ae,0xb428b4db,0xafc2b0ce,0xb196b2ef,0xac18adeb,0xaddfb041,0x9f44a88b,0xa134aa82,0x2a5d2573,0x2c9027cf,0x2ed62d01,0x30eb2f2f,0x31453057,0x339e3242,0x33273235,0x35373481,
0xb20eb30d,0xb452b50d,0xb017b111,0xb1cdb335,0xac50ae3e,0xae18b06a,0x9fa8a8ca,0xa166aac1,0x2ab525bf,0x2cbc280d,0x2f362d47,0x311b2f75,0x318f3094,0x33eb3280,0x338e328d,0x356d34af,
0xb25fb36d,0xb47cb540,0xb04db155,0xb204b37a,0xac89ae90,0xae51b094,0xa006a909,0xa199ab00,0x2b0d260a,0x2ce82833,0x2f952d8c,0x314b2fbb,0x31da30d1,0x341c32be,0x33f532e5,0x35a334dd,
0xb2b1b3cd,0xb4a6b572,0xb084b199,0xb23bb3c0,0xacc2aee3,0xae8ab0be,0xa039a948,0xa1cbab40,0x2b652655,0x2d142859,0x2ff52dd2,0x317c3001,0x3224310e,0x344332fc,0x342e333e,0x35da350c,
0xb303b417,0xb4d1b5a5,0xb0bab1dd,0xb273b403,0xacfbaf36,0xaec3b0e7,0xa06ba987,0xa1fdab7f,0x2bbe26a1,0x2d40287e,0x302a2e18,0x31ac3024,0x326f314b,0x3469333b,0x34633398,0x3612353a,
0xb356b448,0xb4fcb5d9,0xb0f1b221,0xb2aab426,0xad34af88,0xaefcb111,0xa09da9c6,0xa22fabbe,0x2c0b26ec,0x2d6d28a4,0x305a2e5e,0x31dd3047,0x32bb3189,0x3490337a,0x349733f2,0x364a3569,
0xb527b60d,0xb68bb7bd,0xb2e2b449,0xb453b569,0xaf36b13b,0xb081b28d,0xa262abfd,0xa3f4acfb,0x2d9928ca,0x2efc29f8,0x320e306a,0x33983185,0x34b733b9,0x35f934dd,0x36823599,0x382e3722,
0xb553b641,0xb6bab7f5,0xb31ab46d,0xb470b58e,0xaf6fb165,0xb09db2b7,0xa294ac1e,0xa413ad1b,0x2dc528f0,0x2f292a1e,0x323e308d,0x33ca31a9,0x34df33f8,0x362234fe,0x36bb35c9,0x384d3755,
0xb57eb676,0xb6e8b817,0xb352b490,0xb48db5b3,0xafa8b18f,0xb0bab2e2,0xa2c6ac3d,0xa42cad3a,0x2df22915,0x2f552a43,0x326f30b1,0x33fc31cd,0x3506341c,0x364c351f,0x36f535f9,0x386d3789,
0xb5abb6ab,0xb717b834,0xb38bb4b4,0xb4aab5d9,0xafe2b1b9,0xb0d7b30d,0xa2f9ac5d,0xa445ad5a,0x2e1e293b,0x2f822a69,0x32a130d4,0x341731f0,0x352e343c,0x36763540,0x372f3629,0x388d37bd,
0xb5d7b6e0,0xb746b851,0xb3c3b4d8,0xb4c7b5fe,0xb00eb1e3,0xb0f4b338,0xa32bac7d,0xa45fad79,0x2e4b2961,0x2faf2a8f,0x32d230f7,0x34303214,0x3556345c,0x36a03561,0x376a365a,0x38ad37f1,
0xb604b717,0xb775b86f,0xb3fcb4fc,0xb4e4b624,0xb02ab20e,0xb111b363,0xa35dac9c,0xa478ad99,0x2e772987,0x2fdb2ab5,0x3303311b,0x34493238,0x357e347c,0x36ca3582,0x37a5368b,0x38ce3813,
0xb631b74d,0xb7a5b88d,0xb41ab520,0xb501b64a,0xb047b238,0xb12eb38e,0xa38facbc,0xa491adb9,0x2ea329ac,0x30042adb,0x3335313e,0x3463325c,0x35a7349c,0x36f535a3,0x37e236bd,0x38f0382e,
0xb65eb785,0xb7d6b8ab,0xb437b545,0xb51fb670,0xb064b262,0xb14bb3b9,0xa3c2acdb,0xa4aaadd8,0x2ed029d2,0x301a2b00,0x33663162,0x347c3280,0x35d034bd,0x372035c5,0x380f36ef,0x39113849,
0xb803b8ca,0xb8d0b9d0,0xb53cb697,0xb62db7d4,0xb168b3e4,0xb252b4a1,0xa4c3adf8,0xa58caef6,0x30312b26,0x30e42c2b,0x349532a4,0x356433c6,0x374c35e7,0x385a36fc,0x39343865,0x3a5c394d,
0xb81cb8e9,0xb8ebb9f3,0xb55ab6bd,0xb64cb7fd,0xb185b408,0xb26fb4b7,0xa4dcae18,0xa5a5af16,0x30472b4c,0x30fb2c3d,0x34af32c8,0x357e33eb,0x37773609,0x38723720,0x39573880,0x3a84396b,
0xb835b909,0xb906ba17,0xb577b6e4,0xb66bb813,0xb1a2b41e,0xb28db4ce,0xa4f5ae37,0xa5bfaf36,0x305d2b72,0x31112c50,0x34c932ec,0x35993408,0x37a4362b,0x388a3744,0x397a389c,0x3aad398a,
0xb84eb929,0xb922ba3b,0xb595b70b,0xb68ab828,0xb1c0b433,0xb2aab4e4,0xa50fae57,0xa5d8af55,0x30742b98,0x31282c63,0x34e23310,0x35b3341a,0x37d0364d,0x38a23768,0x399e38b9,0x3ad739aa,
0xb868b949,0xb93eba60,0xb5b3b733,0xb6a9b83d,0xb1ddb449,0xb2c8b4fa,0xa528ae77,0xa5f1af75,0x308a2bbe,0x313e2c76,0x34fc3335,0x35ce342d,0x37fd3670,0x38ba378c,0x39c338d6,0x3b0239ca,
0xb881b96a,0xb95aba86,0xb5d2b75b,0xb6c8b852,0xb1fab45f,0xb2e5b511,0xa541ae97,0xa60aaf95,0x30a12be3,0x31552c89,0x35163359,0x35e9343f,0x38153693,0x38d237b1,0x39e838f3,0x3b2d39eb,
0xb89bb98c,0xb977baac,0xb5f0b783,0xb6e8b868,0xb217b475,0xb303b527,0xa55aaeb6,0xa623afb5,0x30b72c05,0x316b2c9c,0x3530337d,0x36043452,0x382c36b6,0x38eb37d6,0x3a0e3910,0x3b593a0c,
0xb8b6b9ae,0xb994bad3,0xb60eb7ab,0xb708b87d,0xb235b48b,0xb321b53e,0xa573aed6,0xa63cafd5,0x30ce2c18,0x31822caf,0x354a33a2,0x361e3464,0x384336d9,0x390437fb,0x3a35392e,0x3b873a2d,
0x214d2216,0x319b326c,0x1f762084,0x2fe830c8,0x1c521de4,0x2c962e40,0x14b6197f,0x250229d7,0x97db8e48,0xa82c9ead,0x9d1b9b12,0xad6bab82,0xa0209ead,0xb05eaf14,0xa1b2a0e9,0xb204b131,
0x27f32890,0x3241332b,0x259826c6,0x306a3156,0x227b246b,0x2d202efb,0x1b122020,0x25982a87,0x9de494b6,0xa8aa9f76,0xa3a8a14d,0xae0eac32,0xa62fa502,0xb0e1afe8,0xa845a75d,0xb2b6b1cc,
0x2aa02b9b,0x32e733e8,0x28aa29a5,0x30e131e5,0x2566275d,0x2daa2fb6,0x1de422df,0x262f2b36,0xa0e997db,0xa927a020,0xa661a46b,0xaeb0aca2,0xa927a82c,0xb163b05e,0xab1daa22,0xb368b266,
0x2ca22d52,0x338d3452,0x2a872be6,0x31563273,0x278f2927,0x2e333039,0x202024cf,0x26c62be6,0xa2df997f,0xa9a5a084,0xa877a62f,0xaf53ad13,0xab36a9d7,0xb1e5b0c8,0xacfaac4b,0xb40cb300,
0x2df52ed6,0x341834b0,0x2c322d13,0x31cc3300,0x28dc2aa0,0x2ebd3096,0x214d262f,0x275d2c4b,0xa46b9b12,0xaa22a0e9,0xa9bea7f3,0xaff5ad84,0xaca2ab82,0xb266b131,0xae65ad84,0xb464b399,
0x2f46302c,0x346a350c,0x2d202e33,0x3241338d,0x29f02c0c,0x2f4630f3,0x227b278f,0x27f32ca2,0xa5669c52,0xaaa0a14d,0xab04a8dc,0xb04badf5,0xadaaac96,0xb2e7b19b,0xafcfaebd,0xb4bcb418,
0x304b30ed,0x34bc3568,0x2e0e2f53,0x32b6340c,0x2b042cc8,0x2fcf3150,0x23a82877,0x28452cfa,0xa6619d1b,0xab1da1b2,0xac25a9be,0xb09cae65,0xaeb0ad6b,0xb368b204,0xb09caff5,0xb512b464,
0x30f331ad,0x350c35c4,0x2efb3039,0x332b3452,0x2c0c2d84,0x302c31ad,0x246b2927,0x28902d52,0xa75d9de4,0xab9ba216,0xacc8aaa0,0xb0edaed6,0xafb6ae40,0xb3e8b26c,0xb150b096,0xb568b4b0,
0x355d361e,0x37c63867,0x339f3497,0x359836b4,0x3071320a,0x32913473,0x28dc2daa,0x2b363032,0xac0ca27b,0xae01a4cf,0xb13eaf46,0xb3bdb163,0xb434b2d5,0xb627b506,0xb5beb4fa,0xb826b73e,
0x35ac3678,0x3808388f,0x340934dd,0x35cf36f5,0x30b53266,0x32d534a0,0x29272e01,0x2b82305e,0xac4ba2df,0xae40a502,0xb18eafb6,0xb406b19b,0xb473b33d,0xb663b539,0xb612b545,0xb84cb784,
0x35fb36d0,0x382c38b7,0x34433521,0x36073736,0x30f932c2,0x331834ce,0x29722e59,0x2bcd308a,0xac89a344,0xae7ea534,0xb1dfb013,0xb42eb1d2,0xb4b3b3a5,0xb6a0b56b,0xb666b58f,0xb872b7c9,
0x36493728,0x385038de,0x347c3565,0x363e3776,0x313e331e,0x335c34fa,0x29be2eb0,0x2c0c30b5,0xacc8a3a8,0xaebda566,0xb22fb04b,0xb455b20a,0xb4f1b406,0xb6dcb59d,0xb6b9b5d8,0xb898b807,
0x3697377e,0x38743904,0x34b635a9,0x367537b6,0x3182337a,0x339f3527,0x2a092f08,0x2c3230e1,0xad07a406,0xaefba598,0xb27fb083,0xb47cb241,0xb530b43a,0xb717b5cf,0xb70cb621,0xb8bdb828,
0x36e437d4,0x3897392a,0x34ee35ed,0x36ab37f5,0x31c633d6,0x33e23554,0x2a542f5f,0x2c57310c,0xad45a439,0xaf3aa5cb,0xb2cfb0bb,0xb4a4b279,0xb56eb46d,0xb752b601,0xb75db669,0xb8e1b84a,
0x37303814,0x38b9394e,0x3527362f,0x36e1381a,0x320a3418,0x34123580,0x2aa02fb6,0x2c7d3137,0xad84a46b,0xaf78a5fd,0xb31eb0f3,0xb4cbb2b0,0xb5acb4a0,0xb78cb632,0xb7adb6b1,0xb905b86b,
0x377c383e,0x38db3972,0x355f3672,0x37173838,0x324e3446,0x343435ac,0x2aeb3007,0x2ca23163,0xadc3a49d,0xafb6a62f,0xb36eb12b,0xb4f1b2e7,0xb5eab4d4,0xb7c6b663,0xb7fdb6f8,0xb928b88b,
0x38fd3996,0x39f33a91,0x374c3857,0x3874393e,0x345535d8,0x355d3730,0x2cc8318e,0x2df532e7,0xaff5a661,0xb0f3a7f3,0xb518b31e,0xb649b46a,0xb800b694,0xb8dbb808,0xb94bb8ab,0xba45b99b,
0x391e39b8,0x3a0f3aad,0x37813875,0x388c3959,0x34763604,0x357d375a,0x2cee31b9,0x2e1a3312,0xb01aa694,0xb112a813,0xb53fb356,0xb66fb485,0xb81cb6c5,0xb8f5b81f,0xb96db8cb,0xba61b9b7,
0x393e39da,0x3a2b3ac7,0x37b63893,0x38a53974,0x3497362f,0x359d3784,0x2d1331e5,0x2e40333d,0xb039a6c6,0xb131a82c,0xb565b38d,0xb694b4a0,0xb838b6f5,0xb90fb836,0xb98eb8ea,0xba7cb9d2,
0x395e39fb,0x3a453ae0,0x37ea38b0,0x38bd398e,0x34b9365b,0x35be37ad,0x2d393210,0x2e653368,0xb058a6f8,0xb150a845,0xb58cb3c3,0xb6b9b4bc,0xb854b725,0xb928b84c,0xb9aeb909,0xba97b9ed,
0x397d3a1b,0x3a5f3af9,0x380f38cd,0x38d539a8,0x34da3686,0x35de37d7,0x2d5e323b,0x2e8b3393,0xb077a72a,0xb16fa85e,0xb5b2b3fa,0xb6deb4d7,0xb870b755,0xb941b863,0xb9ceb927,0xbab0ba07,
0x399b3a3a,0x3a793b10,0x382838ea,0x38ed39c1,0x34fa36b1,0x35fe3800,0x2d843266,0x2eb033bd,0xb096a75d,0xb18ea877,0xb5d8b418,0xb703b4f1,0xb88bb784,0xb95ab879,0xb9edb945,0xbac9ba21,
0x39b93a58,0x3a913b26,0x38423906,0x390439da,0x351b36dc,0x361e3814,0x2daa3291,0x2ed633e8,0xb0b5a78f,0xb1ada890,0xb5feb434,0xb728b50c,0xb8a6b7b3,0xb972b88f,0xba0bb962,0xbae0ba3a,
0x39d73a75,0x3aa93b3c,0x385b3922,0x391b39f2,0x353c3706,0x363e3828,0x2dcf32bc,0x2efb3409,0xb0d4a7c1,0xb1cca8aa,0xb624b44f,0xb74cb527,0xb8c1b7e2,0xb98ab8a5,0xba29b97f,0xbaf7ba52,
0x3ac03b50,0x3b5e3bcb,0x39323a0a,0x39de3ab8,0x365e383c,0x375738d7,0x2f21341f,0x302634c8,0xb1eba8c3,0xb2e1a98c,0xb770b542,0xb846b615,0xb9a2b8bb,0xba51b960,0xbb0dba6a,0xbb9cbb11,
0x3ad73b63,0x3b6e3bd6,0x39493a22,0x39f23acb,0x367d3850,0x377638ea,0x2f463434,0x303934dd,0xb20aa8dc,0xb300a9a5,0xb795b55d,0xb857b62f,0xb9b9b8d0,0xba65b974,0xbb22ba81,0xbba9bb24,
0x3aec3b75,0x3b7d3bdf,0x395f3a39,0x3a063ade,0x369d3864,0x379538fd,0x2f6c3449,0x304b34f1,0xb229a8f5,0xb31ea9be,0xb7b8b577,0xb868b649,0xb9d0b8e5,0xba79b987,0xbb36ba97,0xbbb6bb35,
0x3b013b86,0x3b8c3be7,0x39753a4f,0x3a193af0,0x36bc3878,0x37b3390f,0x2f91345e,0x305e3506,0xb247a90e,0xb33da9d7,0xb7dcb592,0xb879b663,0xb9e7b8fa,0xba8cb99a,0xbb4abaad,0xbbc2bb46,
0x3b153b96,0x3b993bee,0x398a3a65,0x3a2d3b02,0x36dc388b,0x37d13921,0x2fb63473,0x3071351b,0xb266a927,0xb35ca9f0,0xb800b5ac,0xb88ab67d,0xb9fdb90f,0xba9fb9ad,0xbb5cbac3,0xbbccbb56,
0x3b283ba5,0x3ba63bf4,0x39a03a7a,0x3a3f3b13,0x36fb389e,0x37ef3933,0x2fdc3488,0x30833530,0xb285a940,0xb37aaa09,0xb811b5c7,0xb89bb697,0xba12b924,0xbab1b9c0,0xbb6dbad7,0xbbd6bb65,
0x3b3b3bb3,0x3bb23bf9,0x39b53a8f,0x3a523b24,0x371a38b2,0x38073945,0x3001349d,0x30963545,0xb2a4a959,0xb399aa22,0xb823b5e1,0xb8abb6b1,0xba28b938,0xbac3b9d2,0xbb7ebaeb,0xbbdfbb74,
0x3b4d3bc0,0x3bbd3bfc,0x39ca3aa4,0x3a643b34,0x373938c5,0x38153957,0x301334b3,0x30a9355a,0xb2c2a972,0xb3b7aa3b,0xb834b5fb,0xb8bcb6ca,0xba3cb94c,0xbad4b9e4,0xbb8dbaff,0xbbe6bb82,
0x20e921b2,0x31313204,0x1ead2020,0x2f14305e,0x1b121d1b,0x2b822d6b,0xe4817db,0x1ead282c,0x997f94b6,0xa9d7a502,0x9de49c52,0xae40ac96,0xa0849f76,0xb0c8afe8,0xa216a14d,0xb26cb19b,
0x275d2845,0x31cc32b6,0x2502262f,0x2fe830e1,0x214d23a8,0x2c322e0e,0x14b61de4,0x1f7628aa,0xa0209b12,0xaa87a598,0xa46ba27b,0xaefbad20,0xa6c6a598,0xb156b06a,0xa890a7f3,0xb32bb241,
0x2a222b1d,0x32663368,0x282c2927,0x305e3163,0x246b2661,0x2ca22eb0,0x17db20e9,0x20202927,0xa2df9de4,0xab36a62f,0xa75da566,0xafb6adaa,0xa9a5a8aa,0xb1e5b0e1,0xab9baaa0,0xb3e8b2e7,
0x2c4b2cfa,0x3300340c,0x29d72b36,0x30c831e5,0x262f2877,0x2d132f53,0x197f22df,0x208429a5,0xa4cfa020,0xabe6a6c6,0xa927a78f,0xb039ae33,0xabe6aa87,0xb273b156,0xad52aca2,0xb452b38d,
0x2d842e65,0x33993464,0x2b822ca2,0x31313266,0x27f329be,0x2d842ff5,0x1b12246b,0x20e92a22,0xa62fa14d,0xac4ba75d,0xaaa0a8dc,0xb096aebd,0xad13ac32,0xb300b1cc,0xaed6adf5,0xb4b0b418,
0x2ebd2fcf,0x341834bc,0x2c962daa,0x319b32e7,0x28dc2b04,0x2df5304b,0x1c522566,0x214d2aa0,0xa78fa27b,0xaca2a7f3,0xac0ca9f0,0xb0f3af46,0xae33ad20,0xb38db241,0xb02caf46,0xb50cb46a,
0x2ff5309c,0x34643512,0x2d6b2eb0,0x32043368,0x29be2c25,0x2e65309c,0x1d1b2661,0x21b22b1d,0xa877a3a8,0xacfaa845,0xacc8ab04,0xb150afcf,0xaf53ae0e,0xb40cb2b6,0xb0edb04b,0xb568b4bc,
0x30963150,0x34b03568,0x2e402fb6,0x326c33e8,0x2aa02cc8,0x2ed630ed,0x1de4275d,0x22162b9b,0xa927a46b,0xad52a890,0xad84ac0c,0xb1adb02c,0xb039aefb,0xb452b32b,0xb1adb0f3,0xb5c4b50c,
0x34fa35be,0x373e3826,0x32d53434,0x35063627,0x2f46313e,0x316333bd,0x227b2c0c,0x24cf2e01,0xadaaa8dc,0xb032ab36,0xb20ab071,0xb473b291,0xb497b39f,0xb6b4b598,0xb61eb55d,0xb867b7c6,
0x35453612,0x3784384c,0x333d3473,0x35393663,0x2fb6318e,0x319b3406,0x22df2c4b,0x25022e40,0xae01a927,0xb05eab82,0xb266b0b5,0xb4a0b2d5,0xb4ddb409,0xb6f5b5cf,0xb678b5ac,0xb88fb808,
0x358f3666,0x37c93872,0x33a534b3,0x356b36a0,0x301331df,0x31d2342e,0x23442c89,0x25342e7e,0xae59a972,0xb08aabcd,0xb2c2b0f9,0xb4ceb318,0xb521b443,0xb736b607,0xb6d0b5fb,0xb8b7b82c,
0x35d836b9,0x38073898,0x340634f1,0x359d36dc,0x304b322f,0x320a3455,0x23a82cc8,0x25662ebd,0xaeb0a9be,0xb0b5ac0c,0xb31eb13e,0xb4fab35c,0xb565b47c,0xb776b63e,0xb728b649,0xb8deb850,
0x3621370c,0x382838bd,0x343a3530,0x35cf3717,0x3083327f,0x3241347c,0x24062d07,0x25982efb,0xaf08aa09,0xb0e1ac32,0xb37ab182,0xb527b39f,0xb5a9b4b6,0xb7b6b675,0xb77eb697,0xb904b874,
0x3669375d,0x384a38e1,0x346d356e,0x36013752,0x30bb32cf,0x327934a4,0x24392d45,0x25cb2f3a,0xaf5faa54,0xb10cac57,0xb3d6b1c6,0xb554b3e2,0xb5edb4ee,0xb7f5b6ab,0xb7d4b6e4,0xb92ab897,
0x36b137ad,0x386b3905,0x34a035ac,0x3632378c,0x30f3331e,0x32b034cb,0x246b2d84,0x25fd2f78,0xafb6aaa0,0xb137ac7d,0xb418b20a,0xb580b412,0xb62fb527,0xb81ab6e1,0xb814b730,0xb94eb8b9,
0x36f837fd,0x388b3928,0x34d435ea,0x366337c6,0x312b336e,0x32e734f1,0x249d2dc3,0x262f2fb6,0xb007aaeb,0xb163aca2,0xb446b24e,0xb5acb434,0xb672b55f,0xb838b717,0xb83eb77c,0xb972b8db,
0x38ab394b,0x399b3a45,0x36943800,0x380838db,0x331e3518,0x346a3649,0x26612ff5,0x27f330f3,0xb18eacc8,0xb2e7adf5,0xb5d8b455,0xb730b55d,0xb857b74c,0xb93eb874,0xb996b8fd,0xba91b9f3,
0x38cb396d,0x39b73a61,0x36c5381c,0x381f38f5,0x3356353f,0x3485366f,0x2694301a,0x28133112,0xb1b9acee,0xb312ae1a,0xb604b476,0xb75ab57d,0xb875b781,0xb959b88c,0xb9b8b91e,0xbaadba0f,
0x38ea398e,0x39d23a7c,0x36f53838,0x3836390f,0x338d3565,0x34a03694,0x26c63039,0x282c3131,0xb1e5ad13,0xb33dae40,0xb62fb497,0xb784b59d,0xb893b7b6,0xb974b8a5,0xb9dab93e,0xbac7ba2b,
0x390939ae,0x39ed3a97,0x37253854,0x384c3928,0x33c3358c,0x34bc36b9,0x26f83058,0x28453150,0xb210ad39,0xb368ae65,0xb65bb4b9,0xb7adb5be,0xb8b0b7ea,0xb98eb8bd,0xb9fbb95e,0xbae0ba45,
0x392739ce,0x3a073ab0,0x37553870,0x38633941,0x33fa35b2,0x34d736de,0x272a3077,0x285e316f,0xb23bad5e,0xb393ae8b,0xb686b4da,0xb7d7b5de,0xb8cdb80f,0xb9a8b8d5,0xba1bb97d,0xbaf9ba5f,
0x394539ed,0x3a213ac9,0x3784388b,0x3879395a,0x341835d8,0x34f13703,0x275d3096,0x2877318e,0xb266ad84,0xb3bdaeb0,0xb6b1b4fa,0xb800b5fe,0xb8eab828,0xb9c1b8ed,0xba3ab99b,0xbb10ba79,
0x39623a0b,0x3a3a3ae0,0x37b338a6,0x388f3972,0x343435fe,0x350c3728,0x278f30b5,0x289031ad,0xb291adaa,0xb3e8aed6,0xb6dcb51b,0xb814b61e,0xb906b842,0xb9dab904,0xba58b9b9,0xbb26ba91,
0x397f3a29,0x3a523af7,0x37e238c1,0x38a5398a,0x344f3624,0x3527374c,0x27c130d4,0x28aa31cc,0xb2bcadcf,0xb409aefb,0xb706b53c,0xb828b63e,0xb922b85b,0xb9f2b91b,0xba75b9d7,0xbb3cbaa9,
0x3a6a3b0d,0x3b113b9c,0x38bb39a2,0x39603a51,0x35423770,0x36153846,0x28c331eb,0x298c32e1,0xb41faf21,0xb4c8b026,0xb83cb65e,0xb8d7b757,0xba0ab932,0xbab8b9de,0xbb50bac0,0xbbcbbb5e,
0x3a813b22,0x3b243ba9,0x38d039b9,0x39743a65,0x355d3795,0x362f3857,0x28dc320a,0x29a53300,0xb434af46,0xb4ddb039,0xb850b67d,0xb8eab776,0xba22b949,0xbacbb9f2,0xbb63bad7,0xbbd6bb6e,
0x3a973b36,0x3b353bb6,0x38e539d0,0x39873a79,0x357737b8,0x36493868,0x28f53229,0x29be331e,0xb449af6c,0xb4f1b04b,0xb864b69d,0xb8fdb795,0xba39b95f,0xbadeba06,0xbb75baec,0xbbdfbb7d,
0x3aad3b4a,0x3b463bc2,0x38fa39e7,0x399a3a8c,0x359237dc,0x36633879,0x290e3247,0x29d7333d,0xb45eaf91,0xb506b05e,0xb878b6bc,0xb90fb7b3,0xba4fb975,0xbaf0ba19,0xbb86bb01,0xbbe7bb8c,
0x3ac33b5c,0x3b563bcc,0x390f39fd,0x39ad3a9f,0x35ac3800,0x367d388a,0x29273266,0x29f0335c,0xb473afb6,0xb51bb071,0xb88bb6dc,0xb921b7d1,0xba65b98a,0xbb02ba2d,0xbb96bb15,0xbbeebb99,
0x3ad73b6d,0x3b653bd6,0x39243a12,0x39c03ab1,0x35c73811,0x3697389b,0x29403285,0x2a09337a,0xb488afdc,0xb530b083,0xb89eb6fb,0xb933b7ef,0xba7ab9a0,0xbb13ba3f,0xbba5bb28,0xbbf4bba6,
0x3aeb3b7e,0x3b743bdf,0x39383a28,0x39d23ac3,0x35e13823,0x36b138ab,0x295932a4,0x2a223399,0xb49db001,0xb545b096,0xb8b2b71a,0xb945b807,0xba8fb9b5,0xbb24ba52,0xbbb3bb3b,0xbbf9bbb2,
0x3aff3b8d,0x3b823be6,0x394c3a3c,0x39e43ad4,0x35fb3834,0x36ca38bc,0x297232c2,0x2a3b33b7,0xb4b3b013,0xb55ab0a9,0xb8c5b739,0xb957b815,0xbaa4b9ca,0xbb34ba64,0xbbc0bb4d,0xbbfcbbbd,
0x39b839ba,0x3a973ab5,0x39b339b5,0x3a583a78,0x39af39b1,0x3a153a37,0x39aa39ad,0x39cd39f2,0x39a639a8,0x398239a8,0x39a139a4,0x3933395b,0x399d399f,0x38e03909,0x3999399b,0x388938b5,
0xb979b972,0xb865b832,0xb986b980,0xb8c7b896,0xb994b98d,0xb924b8f6,0xb9a1b99b,0xb97db951,0xb9afb9a8,0xb9d2b9a8,0xb9bcb9b5,0xba21b9fa,0xb9c9b9c3,0xba6bba47,0xb9d6b9d0,0xbab0ba8e,
0xb9f4b9fe,0xbac7bae9,0xb9dfb9e9,0xba7ebaa3,0xb9c9b9d4,0xba2dba56,0xb9b3b9be,0xb9d6ba02,0xb99db9a8,0xb979b9a8,0xb986b992,0xb916b948,0xb970b97b,0xb8adb8e2,0xb958b964,0xb840b877,
0x39373927,0x381a37b7,0x39583948,0x38943858,0x39793969,0x390738ce,0x39993989,0x3974393e,0x39b839a8,0x39da39a8,0x39d639c7,0x3a393a0b,0x39f439e5,0x3a903a65,0x3a113a02,0x3ade3ab8,
0x3a2d3a3f,0x3af43b1a,0x3a093a1b,0x3aa23acc,0x39e339f6,0x3a453a74,0x39bc39d0,0x39df3a13,0x399439a8,0x397039a8,0x396b3980,0x38f83935,0x39413956,0x387a38ba,0x3916392b,0x37e83838,
0xb8f3b8d8,0xb79bb705,0xb929b90e,0xb85fb817,0xb95db943,0xb8eab8a6,0xb990b976,0xb96bb92b,0xb9c0b9a8,0xb9e3b9a8,0xb9f0b9d8,0xba50ba1b,0xba1dba07,0xbab3ba83,0xba49ba33,0xbb0abae0,
0xba64ba7c,0xbb1ebb46,0xba31ba4b,0xbac4baf3,0xb9fcba17,0xba5cba92,0xb9c5b9e1,0xb9e7ba23,0xb98bb9a8,0xb966b9a8,0xb94fb96d,0xb8dbb922,0xb911b930,0xb845b891,0xb8d1b8f1,0xb74eb7ee,
0x38ad3887,0x36ff364e,0x38f838d3,0x382a37ac,0x3941391d,0x38cc387c,0x39863964,0x39623918,0x39c939a8,0x39eb39a8,0x3a0939e9,0x3a673a2b,0x3a453a27,0x3ad53aa0,0x3a7e3a62,0x3b323b05,
0x3b453b6e,0x3bbc3bdd,0x3ae53b17,0x3b573b8f,0x3a733aae,0x3ac73b14,0x39f03a33,0x3a113a71,0x395d39a8,0x393739a8,0x38bc390e,0x384038bf,0x380f3867,0x365f3775,0x36af376a,0x341a3540,
0xb65fb593,0xb389b115,0xb7e8b726,0xb625b4f9,0xb8adb852,0xb830b748,0xb958b905,0xb933b8b5,0xb9f4b9a8,0xba15b9a8,0xba7eba3b,0xbad1ba78,0xbaf4babc,0xbb63bb20,0xbb57bb28,0xbbc6bb9b,
0xbb68bb91,0xbbd0bbed,0xbb04bb39,0xbb6fbba6,0xba89bac9,0xbadbbb2b,0xb9f8ba43,0xba19ba7f,0xb954b9a8,0xb92eb9a8,0xb89eb8fb,0xb820b8ab,0xb7b2b83d,0xb5ebb71b,0xb60eb6e3,0xb2deb4b1,
0x35bc34d5,0x32322f0e,0x377a369e,0x35b13469,0x388e3828,0x380f36ee,0x394f38f1,0x392938a0,0x39fc39a8,0x3a1d39a8,0x3a933a4b,0x3ae53a87,0x3b133ad6,0x3b7a3b36,0x3b783b49,0x3bd93bb1,
0x3b873baf,0x3be13bf8,0x3b213b58,0x3b853bbb,0x3a9e3ae3,0x3aee3b41,0x3a003a52,0x3a213a8e,0x394a39a8,0x392439a8,0x387f38e7,0x37fe3896,0x37423812,0x357636c1,0x356a3659,0x31853420,
0xb517b414,0xb0d7abd9,0xb70ab614,0xb53ab3ae,0xb86fb7f9,0xb7ddb693,0xb946b8dd,0xb91fb88c,0xba04b9a8,0xba25b9a8,0xbaa9ba5a,0xbaf7ba95,0xbb2fbaf0,0xbb90bb4b,0xbb96bb67,0xbbe8bbc4,
0xbba3bbc9,0xbbefbbff,0xbb3dbb74,0xbb9abbcd,0xbab3bafc,0xbb01bb55,0xba09ba62,0xba29ba9c,0xb941b9a8,0xb91bb9a8,0xb85fb8d3,0xb7bdb881,0xb6d2b7cd,0xb4ffb665,0xb4c3b5ce,0xb029b31b,
0x346f32a1,0x2ef52248,0x36993587,0x34c33288,0x385037a1,0x379b3637,0x393c38c9,0x39163877,0x3a0d39a8,0x3a2d39a8,0x3abd3a69,0x3b0a3aa3,0x3b4a3b08,0x3ba33b5f,0x3bb03b82,0x3bf43bd5,
0x3bf83c00,0x3bf93bd4,0x3bac3bdc,0x3be43bfe,0x3b133b69,0x3b543bab,0x3a313aaa,0x3a503ae0,0x391139a8,0x38ea39a8,0x377a386d,0x366b3817,0x34873608,0x313b348d,0x2d9731f4,0xad65291b,
0xac3828b6,0x2ec33365,0xb44bb160,0xb0bea57f,0xb759b5da,0xb648b45d,0xb90cb862,0xb8e5b80d,0xba35b9a8,0xba54b9a8,0xbb1bbab1,0xbb5cbae6,0xbbb5bb72,0xbbe9bbb2,0xbbfcbbe3,0xbbf5bc00,
0xbbfebbfc,0xbbefbbbc,0xbbbdbbe9,0xbbeebc00,0xbb24bb7b,0xbb63bbb9,0xba39bab8,0xba58baed,0xb907b9a8,0xb8e0b9a8,0xb737b858,0xb625b802,0xb40eb5ab,0xb042b42c,0xa9b1b0cb,0x30109a48,
0x25e4ad7e,0xb0beb475,0x33a23036,0x2f8ba3db,0x3715357c,0x360233f7,0x3902384d,0x38db37ee,0x3a3d39a8,0x3a5c39a8,0x3b2c3abf,0x3b6a3af3,0x3bc53b84,0x3bf23bc0,0x3bff3bee,0x3be93c00,
0x3c003bf4,0x3be23ba0,0x3bcc3bf3,0x3bf53bff,0x3b353b8c,0x3b713bc6,0x3a413ac6,0x3a603af9,0x38fd39a8,0x38d639a8,0x36f43842,0x35df37d8,0x3328354c,0x2e913396,0x16482f40,0xb16ca852,
0x251b304e,0x32193534,0xb2adae14,0xad972aac,0xb6d2b51d,0xb5bcb334,0xb8f8b838,0xb8d1b7c2,0xba45b9a8,0xba64b9a8,0xbb3dbacc,0xbb78baff,0xbbd3bb95,0xbbf8bbcb,0xbc00bbf7,0xbbdabbfd,
0xbbfebbe6,0xbbd2bb80,0xbbd9bbfa,0xbbfbbbfb,0xbb45bb9d,0xbb7fbbd1,0xba49bad3,0xba67bb05,0xb8f3b9a8,0xb8ccb9a8,0xb6afb82d,0xb599b7ac,0xb232b4ed,0xac9cb2d2,0x294dace7,0x32c62c83,
0xac06b1db,0xb371b5f1,0x31b62b75,0x2b43adb0,0x368d34bd,0x3576326f,0x38ee3822,0x38c73796,0x3a4d39a8,0x3a6b39a8,0x3b4c3ad9,0x3b853b0b,0x3bdf3ba4,0x3bfd3bd6,0x3bfc3bfd,0x3bc83bf8,
0x3bbd3b5a,0x3b473a99,0x3bfe3bf4,0x3bf93bbe,0x3b8b3bdb,0x3bb83bf7,0x3a6f3b11,0x3a8c3b3e,0x38c139a8,0x389939a8,0x35523780,0x343236cc,0x294d320d,0xad332de2,0xb40eaedc,0xb6a4b408,
0x346336aa,0x36f438b0,0xa6ad3004,0x2e2d3451,0xb52fb1aa,0xb40ead1a,0xb8bcb76a,0xb894b6b5,0xba73b9a8,0xba90b9a8,0xbb92bb17,0xbbbdbb43,0xbbffbbe0,0xbbf6bbf9,0xbbb2bbf0,0xbb35bbb4,
0xbba5bb30,0xbb21ba5e,0xbc00bbeb,0xbbf3bbaa,0xbb98bbe4,0xbbc2bbfb,0xba76bb1d,0xba93bb49,0xb8b7b9a8,0xb88eb9a8,0xb50bb753,0xb3d3b69e,0xa17fb147,0x2f27ac51,0x34b73099,0x37423499,
0xb50bb75e,0xb790b900,0x9cb6b12e,0xb010b4e1,0x34e730e4,0x33892b11,0x38b2373d,0x38893687,0x3a7a39a8,0x3a9739a8,0x3b9e3b22,0x3bc63b4e,0x3c003be8,0x3bef3bfd,0x3b983be5,0x3b0d3b9e,
0x3b893b02,0x3af73a1f,0x3c003bdf,0x3beb3b93,0x3ba33bec,0x3bcb3bfe,0x3a7e3b28,0x3a9b3b53,0x38ad39a8,0x388439a8,0x34c33726,0x33403670,0xa51b3080,0xb08d297f,0xb55eb1c3,0xb7ddb529,
0x35b13807,0x3815394d,0x28843257,0x31093570,0xb49fb01d,0xb2f7a7da,0xb8a8b710,0xb87fb659,0xba81b9a8,0xba9eb9a8,0xbba9bb2e,0xbbcfbb58,0xbbffbbef,0xbbe6bbff,0xbb7abbd7,0xbae1bb86,
0xbb6abad0,0xbacbb9dc,0xbbfdbbd0,0xbbe1bb79,0xbbaebbf2,0xbbd3bc00,0xba85bb33,0xbaa2bb5d,0xb8a3b9a8,0xb87ab9a8,0xb47bb6f9,0xb2adb642,0x2a7aaf72,0x3185a4b6,0x360232ea,0x383a35b6,
0xb654b85d,0xb85fb996,0xac38b37d,0xb201b5fd,0x34572eaa,0x32631e48,0x389e36e3,0x3874362b,0x3a8939a8,0x3aa539a8,0x3bb33b39,0x3bd73b62,0x3bfc3bf5,0x3bdc3c00,0x3b593bc7,0x3ab33b6b,
0x39b739b9,0x3a883aa6,0x39b239b4,0x3a483a68,0x39ae39b0,0x3a033a26,0x39a939ab,0x39bb39e0,0x39a539a7,0x396e3995,0x39a039a3,0x391e3947,0x399c399e,0x38ca38f5,0x3997399a,0x3873389f,
0xb97cb975,0xb87eb84c,0xb98ab983,0xb8deb8ae,0xb997b991,0xb93bb90d,0xb9a5b99e,0xb993b967,0xb9b2b9ab,0xb9e6b9bd,0xb9bfb9b9,0xba34ba0e,0xb9ccb9c6,0xba7dba59,0xb9d9b9d3,0xbac0ba9f,
0xb9efb9f9,0xbab6bad9,0xb9d9b9e4,0xba6aba91,0xb9c4b9cf,0xba18ba42,0xb9aeb9b9,0xb9bfb9ec,0xb997b9a3,0xb961b991,0xb981b98c,0xb8fcb92f,0xb96ab975,0xb892b8c8,0xb953b95e,0xb824b85c,
0x3940392f,0x383937f6,0x39613950,0x38b13876,0x39813971,0x392338eb,0x39a03991,0x398e395a,0x39bf39b0,0x39f339c1,0x39de39cf,0x3a4f3a22,0x39fb39ec,0x3aa43a7b,0x3a183a0a,0x3af03acb,
0x3a243a36,0x3ae13b07,0x39ff3a12,0x3a8b3ab7,0x39d939ec,0x3a2c3a5d,0x39b239c6,0x39c439f9,0x398a399e,0x3953398c,0x39613975,0x38d93917,0x3936394b,0x3859389a,0x390b3921,0x37a43816,
0xb901b8e6,0xb7e6b750,0xb936b91c,0xb883b83c,0xb96ab950,0xb90bb8c8,0xb99cb983,0xb98ab94b,0xb9ccb9b4,0xb9ffb9c6,0xb9fbb9e4,0xba6aba36,0xba28ba12,0xbacaba9b,0xba53ba3e,0xbb1dbaf5,
0xba57ba70,0xbb09bb33,0xba24ba3e,0xbaabbadc,0xb9efba0a,0xba40ba77,0xb9b7b9d3,0xb9c8ba05,0xb97cb99a,0xb944b988,0xb940b95e,0xb8b6b8fe,0xb901b921,0xb81eb86b,0xb8c0b8e1,0xb6fcb79e,
0x38c0389a,0x375636a7,0x390b38e6,0x38543800,0x3953392f,0x38f238a4,0x39973975,0x3985393d,0x39d939b9,0x3a0c39ca,0x3a1839f9,0x3a843a4a,0x3a533a36,0x3aed3abb,0x3a8b3a70,0x3b473b1c,
0x3b2e3b5a,0x3ba63bce,0x3aca3afe,0x3b373b74,0x3a533a91,0x3a9d3aef,0x39cc3a12,0x39de3a42,0x39363983,0x38fc3971,0x389238e6,0x37fb3880,0x37c5383c,0x35d136eb,0x3651370d,0x330934ae,
0xb6c3b5fa,0xb460b251,0xb824b788,0xb6b8b590,0xb8d9b880,0xb873b7d5,0xb981b92f,0xb96eb8f5,0xba18b9cf,0xba48b9e0,0xba9dba5d,0xbafabaa6,0xbb0fbad9,0xbb80bb43,0xbb6cbb40,0xbbd8bbb2,
0xbb51bb7d,0xbbbdbbe0,0xbae7bb1f,0xbb4ebb8c,0xba66baa9,0xbaafbb04,0xb9d1ba1e,0xb9e2ba4e,0xb928b97e,0xb8edb96c,0xb86eb8cd,0xb7afb866,0xb74bb80b,0xb54fb684,0xb5a2b679,0xb197b411,
0x362e3549,0x338330de,0x37e6370d,0x3651350e,0x38c0385c,0x38593788,0x397c3921,0x396a38e6,0x3a2439d3,0x3a5339e4,0x3ab63a70,0x3b0f3ab7,0x3b2e3af5,0x3b973b5a,0x3b8d3b61,0x3be83bc7,
0x3b703b9c,0x3bd03bef,0x3b033b3d,0x3b653ba2,0x3a793ac1,0x3ac03b19,0x39d53a2a,0x39e63a59,0x3919397a,0x38de3967,0x384938b4,0x3761384c,0x36cf37b4,0x34cc361d,0x34f035e2,0x302332e4,
0xb596b496,0xb244aecf,0xb783b690,0xb5e8b48a,0xb8a7b836,0xb83eb73a,0xb978b912,0xb965b8d7,0xba30b9d7,0xba5fb9e8,0xbacdba82,0xbb23bac8,0xbb4cbb10,0xbbacbb6f,0xbbaabb7f,0xbbf4bbd8,
0xbb8dbbb7,0xbbe0bbf9,0xbb1dbb5a,0xbb7abbb5,0xba8bbad9,0xbad0bb2d,0xb9d9ba36,0xb9eaba65,0xb90bb975,0xb8cfb963,0xb824b89a,0xb713b831,0xb651b750,0xb447b5b3,0xb43bb549,0xad58b1a4,
0x34fc33c0,0x31032bc0,0x371e3611,0x357e3405,0x388d3811,0x382436eb,0x39733903,0x396138c8,0x3a3c39db,0x3a6a39ec,0x3ae43a94,0x3b373ad9,0x3b673b2a,0x3bbe3b83,0x3bc33b9a,0x3bfc3be7,
0x3bed3bff,0x3bff3bea,0x3b8d3bc7,0x3bcc3bf5,0x3ae13b40,0x3b1d3b83,0x39ef3a70,0x39ff3a9b,0x38c0395e,0x3883394b,0x36c33816,0x357e3750,0x33833549,0x2e84332e,0x28cf3061,0xb0aca5b2,
0xaf7ea376,0x29663166,0xb514b2fd,0xb2bfad71,0xb809b69b,0xb734b555,0xb95cb8b9,0xb949b87b,0xba75b9f1,0xbaa1ba01,0xbb49bae9,0xbb8bbb25,0xbbcfbb96,0xbbf9bbd2,0xbc00bbf2,0xbbe3bbfe,
0xbbf6bc00,0xbbfcbbda,0xbb9fbbd6,0xbbd8bbfb,0xbaf0bb52,0xbb2cbb92,0xb9f3ba7b,0xba03baa6,0xb8b1b95a,0xb873b947,0xb673b7f6,0xb52cb718,0xb276b4de,0xac5eb251,0x2052ae39,0x321f2bf2,
0x2cf4a806,0xad3fb2d8,0x34a831ee,0x31e22a93,0x37db364b,0x36fc3502,0x395738a9,0x3944386b,0x3a8039f5,0x3aab3a05,0x3b5b3af8,0x3b993b33,0x3bdd3ba7,0x3bfd3bdd,0x3bff3bfa,0x3bd13bf9,
0x3bfd3bfd,0x3bf53bc6,0x3baf3be3,0x3be23bff,0x3b003b64,0x3b393ba0,0x39f73a86,0x3a083ab0,0x38a23955,0x38633942,0x362237bf,0x34d836e0,0x31663472,0x286b3172,0xaaf82b5c,0xb390ae84,
0xa8cf2cf4,0x2fc93423,0xb43bb0de,0xb103a484,0xb7a4b5fa,0xb6c3b4ae,0xb953b89a,0xb940b85c,0xba8bb9f9,0xbab6ba0a,0xbb6cbb07,0xbba6bb40,0xbbe8bbb7,0xbc00bbe7,0xbbfabbff,0xbbbabbf1,
0xbc00bbf6,0xbbebbbae,0xbbbebbed,0xbbebbc00,0xbb0fbb74,0xbb47bbad,0xb9fbba91,0xba0cbabb,0xb892b950,0xb854b93d,0xb5d1b788,0xb484b6a7,0xb055b405,0x9248b093,0x2e6ba484,0x347e3086,
0x98b6afe2,0xb128b4d8,0x339c2f97,0x3023a420,0x376c35a8,0x368a345a,0x394e388b,0x393b384c,0x3a9639fd,0x3ac03a0e,0x3b7c3b16,0x3bb33b4d,0x3bf23bc5,0x3c003bef,0x3bf03c00,0x3ba03be5,
0x3bde3b91,0x3b8a3af7,0x3bf23bff,0x3c003be3,0x3b533bb9,0x3b823bdf,0x3a103ac5,0x3a203aec,0x38443939,0x38033925,0x342f366d,0x31b03584,0xa8392f65,0xb15a1d7f,0xb531b1c9,0xb7e0b55b,
0x3269358a,0x35a83819,0xae842a61,0x205231e2,0xb651b405,0xb567b15a,0xb936b83c,0xb923b7f6,0xbacaba12,0xbaf0ba22,0xbbbebb5a,0xbbe3bb88,0xbbfdbbf5,0xbbddbc00,0xbb81bbd6,0xbadfbb7c,
0xbbcebb70,0xbb6dbac6,0xbbf8bbfb,0xbbffbbd6,0xbb60bbc4,0xbb8dbbe7,0xba14bacf,0xba24baf5,0xb834b934,0xb7e6b921,0xb3b4b634,0xb103b549,0x2c44ada3,0x326925b2,0x35e23309,0x384135f4,
0xb3a8b63a,0xb63fb869,0x2cc2ad58,0xa89db2f0,0x3617335f,0x352c30ac,0x3931382c,0x391e37d5,0x3ad43a16,0x3afa3a26,0x3bc93b66,0x3bea3b92,0x3bf93bfa,0x3bcf3bff,0x3b5f3bc5,0x3aad3b5d,
0x3bba3b4c,0x3b4d3a93,0x3bfc3bf6,0x3bfd3bc7,0x3b6c3bce,0x3b973bed,0x3a183ad9,0x3a283afe,0x3824392f,0x37c5391c,0x330935fa,0x3055350e,0xae6b2bc0,0xb377aa61,0xb690b423,0xb890b68a,
0x347236e5,0x36d438b6,0xa9fd2f7e,0x2c1233fd,0xb5dcb2b3,0xb4f0affb,0xb92db81c,0xb919b7b4,0xbaddba1a,0xbb03ba2a,0xbbd3bb72,0xbbf0bb9c,0xbbf2bbfe,0xbbbfbbfc,0xbb38bbaf,0xba77bb3c,
0xbba4bb23,0xbb2aba5b,0xbbffbbee,0xbbfabbb6,0xbb77bbd7,0xbba1bbf3,0xba1cbae2,0xba2cbb07,0xb813b92a,0xb7a4b917,0xb25db5bf,0xaf4cb4d2,0x3048a839,0x34412cf4,0x373a34c0,0x38dc371e,
0xb50eb78e,0xb767b901,0x24e9b0d1,0xadd5b484,0x35a23207,0x34b42e9d,0x3928380b,0x39143793,0x3ae73a1e,0x3b0c3a2e,0x3bdb3b7d,0x3bf53ba6,0x3be93c00,0x3bad3bf7,0x3b0d3b97,0x3a3e3b18,
0xb999b996,0xb889b85d,0xb99db99b,0xb8e0b8b5,0xb9a1b99f,0xb933b909,0xb9a6b9a4,0xb982b95b,0xb9aab9a8,0xb9cdb9a8,0xb9afb9ad,0xba15b9f2,0xb9b3b9b1,0xba58ba37,0xb9b8b9b5,0xba97ba78,
0xb9d6b9dc,0xbab0bad0,0xb9c9b9d0,0xba6bba8e,0xb9bcb9c3,0xba21ba47,0xb9afb9b5,0xb9d2b9fa,0xb9a1b9a8,0xb97db9a8,0xb994b99b,0xb924b951,0xb986b98d,0xb8c7b8f6,0xb979b980,0xb865b896,
0x3958394d,0x38403807,0x39703964,0x38ad3877,0x3986397b,0x391638e2,0x399d3992,0x39793948,0x39b339a8,0x39d639a8,0x39c939be,0x3a2d3a02,0x39df39d4,0x3a7e3a56,0x39f439e9,0x3ac73aa3,
0x3a113a1f,0x3ade3b02,0x39f43a02,0x3a903ab8,0x39d639e5,0x3a393a65,0x39b839c7,0x39da3a0b,0x399939a8,0x397439a8,0x39793989,0x3907393e,0x39583969,0x389438ce,0x39373948,0x381a3858,
0xb916b900,0xb7e8b75e,0xb941b92b,0xb87ab838,0xb96bb956,0xb8f8b8ba,0xb994b980,0xb970b935,0xb9bcb9a8,0xb9dfb9a8,0xb9e3b9d0,0xba45ba13,0xba09b9f6,0xbaa2ba74,0xba2dba1b,0xbaf4bacc,
0xba49ba5e,0xbb0abb30,0xba1dba33,0xbab3bae0,0xb9f0ba07,0xba50ba83,0xb9c0b9d8,0xb9e3ba1b,0xb990b9a8,0xb96bb9a8,0xb95db976,0xb8eab92b,0xb929b943,0xb85fb8a6,0xb8f3b90e,0xb79bb817,
0x38d138b0,0x374e36aa,0x391138f1,0x384537ee,0x394f3930,0x38db3891,0x398b396d,0x39663922,0x39c539a8,0x39e739a8,0x39fc39e1,0x3a5c3a23,0x3a313a17,0x3ac43a92,0x3a643a4b,0x3b1e3af3,
0x3a7e3a99,0x3b323b5a,0x3a453a62,0x3ad53b05,0x3a093a27,0x3a673aa0,0x39c939e9,0x39eb3a2b,0x398639a8,0x396239a8,0x39413964,0x38cc3918,0x38f8391d,0x382a387c,0x38ad38d3,0x36ff37ac,
0xb6afb5f1,0xb41ab1db,0xb80fb76a,0xb65fb540,0xb8bcb867,0xb840b775,0xb95db90e,0xb937b8bf,0xb9f0b9a8,0xba11b9a8,0xba73ba33,0xbac7ba71,0xbae5baae,0xbb57bb14,0xbb45bb17,0xbbbcbb8f,
0xbb57bb80,0xbbc6bbe6,0xbaf4bb28,0xbb63bb9b,0xba7ebabc,0xbad1bb20,0xb9f4ba3b,0xba15ba78,0xb958b9a8,0xb933b9a8,0xb8adb905,0xb830b8b5,0xb7e8b852,0xb625b748,0xb65fb726,0xb389b4f9,
0x360e3534,0x32de304e,0x37b236e3,0x35eb34b1,0x389e383d,0x3820371b,0x395438fb,0x392e38ab,0x39f839a8,0x3a1939a8,0x3a893a43,0x3adb3a7f,0x3b043ac9,0x3b6f3b2b,0x3b683b39,0x3bd03ba6,
0x3b783ba0,0x3bd93bf4,0x3b133b49,0x3b7a3bb1,0x3a933ad6,0x3ae53b36,0x39fc3a4b,0x3a1d3a87,0x394f39a8,0x392939a8,0x388e38f1,0x380f38a0,0x377a3828,0x35b136ee,0x35bc369e,0x32323469,
0xb56ab475,0xb185ad7e,0xb742b659,0xb576b420,0xb87fb812,0xb7feb6c1,0xb94ab8e7,0xb924b896,0xba00b9a8,0xba21b9a8,0xba9eba52,0xbaeeba8e,0xbb21bae3,0xbb85bb41,0xbb87bb58,0xbbe1bbbb,
0xbb96bbbc,0xbbe8bbfc,0xbb2fbb67,0xbb90bbc4,0xbaa9baf0,0xbaf7bb4b,0xba04ba5a,0xba25ba95,0xb946b9a8,0xb91fb9a8,0xb86fb8dd,0xb7ddb88c,0xb70ab7f9,0xb53ab693,0xb517b614,0xb0d7b3ae,
0x34c33365,0x302928b6,0x36d235ce,0x34ff331b,0x385f37cd,0x37bd3665,0x394138d3,0x391b3881,0x3a0939a8,0x3a2939a8,0x3ab33a62,0x3b013a9c,0x3b3d3afc,0x3b9a3b55,0x3ba33b74,0x3bef3bcd,
0x3bb03bd4,0x3bf43c00,0x3b4a3b82,0x3ba33bd5,0x3abd3b08,0x3b0a3b5f,0x3a0d3a69,0x3a2d3aa3,0x393c39a8,0x391639a8,0x385038c9,0x379b3877,0x369937a1,0x34c33637,0x346f3587,0x2ef53288,
0xad972248,0x2d6532a1,0xb487b1f4,0xb13ba91b,0xb77ab608,0xb66bb48d,0xb911b86d,0xb8eab817,0xba31b9a8,0xba50b9a8,0xbb13baaa,0xbb54bae0,0xbbacbb69,0xbbe4bbab,0xbbf8bbdc,0xbbf9bbfe,
0xbbfcbbff,0xbbf5bbc9,0xbbb5bbe3,0xbbe9bc00,0xbb1bbb72,0xbb5cbbb2,0xba35bab1,0xba54bae6,0xb90cb9a8,0xb8e5b9a8,0xb759b862,0xb648b80d,0xb44bb5da,0xb0beb45d,0xac38b160,0x2ec3a57f,
0x29b1abd9,0xb010b414,0x340e30cb,0x30421a48,0x373735ab,0x3625342c,0x39073858,0x38e03802,0x3a3939a8,0x3a5839a8,0x3b243ab8,0x3b633aed,0x3bbd3b7b,0x3bee3bb9,0x3bfe3be9,0x3bef3c00,
0x3bff3bf8,0x3be93baf,0x3bc53bee,0x3bf23c00,0x3b2c3b84,0x3b6a3bc0,0x3a3d3abf,0x3a5c3af3,0x390239a8,0x38db39a8,0x3715384d,0x360237ee,0x33a2357c,0x2f8b33f7,0x25e43036,0xb0bea3db,
0x96482f0e,0x316c34d5,0xb328af40,0xae912852,0xb6f4b54c,0xb5dfb396,0xb8fdb842,0xb8d6b7d8,0xba41b9a8,0xba60b9a8,0xbb35bac6,0xbb71baf9,0xbbccbb8c,0xbbf5bbc6,0xbc00bbf3,0xbbe2bbff,
0xbc00bbed,0xbbdabb91,0xbbd3bbf7,0xbbf8bbfd,0xbb3dbb95,0xbb78bbcb,0xba45bacc,0xba64baff,0xb8f8b9a8,0xb8d1b9a8,0xb6d2b838,0xb5bcb7c2,0xb2adb51d,0xad97b334,0x251bae14,0x32192aac,
0xa94db115,0xb2c6b593,0x32322ce7,0x2c9cac83,0x36af34ed,0x359932d2,0x38f3382d,0x38cc37ac,0x3a4939a8,0x3a6739a8,0x3b453ad3,0x3b7f3b05,0x3bd93b9d,0x3bfb3bd1,0x3bfe3bfa,0x3bd23bfb,
0x3bfc3bdd,0x3bc83b6e,0x3bdf3bfd,0x3bfd3bf8,0x3b4c3ba4,0x3b853bd6,0x3a4d3ad9,0x3a6b3b0b,0x38ee39a8,0x38c739a8,0x368d3822,0x35763796,0x31b634bd,0x2b43326f,0xac062b75,0xb371adb0,
0x340e364e,0x36a43887,0xa94d2edc,0x2d333408,0xb552b20d,0xb432ade2,0xb8c1b780,0xb899b6cc,0xba6fb9a8,0xba8cb9a8,0xbb8bbb11,0xbbb8bb3e,0xbbfebbdb,0xbbf9bbf7,0xbbbdbbf4,0xbb47bbbe,
0xbbb2bb46,0xbb35ba7c,0xbbffbbf0,0xbbf6bbb4,0xbb92bbe0,0xbbbdbbf9,0xba73bb17,0xba90bb43,0xb8bcb9a8,0xb894b9a8,0xb52fb76a,0xb40eb6b5,0xa6adb1aa,0x2e2dad1a,0x34633004,0x36f43451,
0xb4b7b705,0xb742b8d8,0x217fb099,0xaf27b499,0x350b3147,0x33d32c51,0x38b73753,0x388e369e,0x3a7639a8,0x3a9339a8,0x3b983b1d,0x3bc23b49,0x3c003be4,0x3bf33bfb,0x3ba53beb,0x3b213baa,
0x3b983b1a,0x3b0d3a3f,0x3c003be5,0x3bef3b9e,0x3b9e3be8,0x3bc63bfd,0x3a7a3b22,0x3a973b4e,0x38b239a8,0x388939a8,0x34e7373d,0x33893687,0x9cb630e4,0xb0102b11,0xb50bb12e,0xb790b4e1,
0x355e37b7,0x37dd3927,0x251b31c3,0x308d3529,0xb4c3b080,0xb340a97f,0xb8adb726,0xb884b670,0xba7eb9a8,0xba9bb9a8,0xbba3bb28,0xbbcbbb53,0xbc00bbec,0xbbebbbfe,0xbb89bbdf,0xbaf7bb93,
0xbb7abae9,0xbae1b9fe,0xbbffbbd7,0xbbe6bb86,0xbba9bbef,0xbbcfbbff,0xba81bb2e,0xba9ebb58,0xb8a8b9a8,0xb87fb9a8,0xb49fb710,0xb2f7b659,0x2884b01d,0x3109a7da,0x35b13257,0x38153570,
0xb602b832,0xb83ab972,0xaa7ab2ea,0xb185b5b6,0x347b2f72,0x32ad24b6,0x38a336f9,0x387a3642,0x3a8539a8,0x3aa239a8,0x3bae3b33,0x3bd33b5d,0x3bfd3bf2,0x3be13c00,0x3b6a3bd0,0x3acb3b79,
0x3b593ab5,0x3ab339ba,0x3bfc3bc7,0x3bdc3b6b,0x3bb33bf5,0x3bd73c00,0x3a893b39,0x3aa53b62,0x389e39a8,0x387439a8,0x345736e3,0x3263362b,0xac382eaa,0xb2011e48,0xb654b37d,0xb85fb5fd,
0xb99ab997,0xb89fb873,0xb99eb99c,0xb8f5b8ca,0xb9a3b9a0,0xb947b91e,0xb9a7b9a5,0xb995b96e,0xb9abb9a9,0xb9e0b9bb,0xb9b0b9ae,0xba26ba03,0xb9b4b9b2,0xba68ba48,0xb9b9b9b7,0xbaa6ba88,
0xb9d3b9d9,0xba9fbac0,0xb9c6b9cc,0xba59ba7d,0xb9b9b9bf,0xba0eba34,0xb9abb9b2,0xb9bdb9e6,0xb99eb9a5,0xb967b993,0xb991b997,0xb90db93b,0xb983b98a,0xb8aeb8de,0xb975b97c,0xb84cb87e,
0x395e3953,0x385c3824,0x3975396a,0x38c83892,0x398c3981,0x392f38fc,0x39a33997,0x39913961,0x39b939ae,0x39ec39bf,0x39cf39c4,0x3a423a18,0x39e439d9,0x3a913a6a,0x39f939ef,0x3ad93ab6,
0x3a0a3a18,0x3acb3af0,0x39ec39fb,0x3a7b3aa4,0x39cf39de,0x3a223a4f,0x39b039bf,0x39c139f3,0x399139a0,0x395a398e,0x39713981,0x38eb3923,0x39503961,0x387638b1,0x392f3940,0x37f63839,
0xb921b90b,0xb816b7a4,0xb94bb936,0xb89ab859,0xb975b961,0xb917b8d9,0xb99eb98a,0xb98cb953,0xb9c6b9b2,0xb9f9b9c4,0xb9ecb9d9,0xba5dba2c,0xba12b9ff,0xbab7ba8b,0xba36ba24,0xbb07bae1,
0xba3eba53,0xbaf5bb1d,0xba12ba28,0xba9bbaca,0xb9e4b9fb,0xba36ba6a,0xb9b4b9cc,0xb9c6b9ff,0xb983b99c,0xb94bb98a,0xb950b96a,0xb8c8b90b,0xb91cb936,0xb83cb883,0xb8e6b901,0xb750b7e6,
0x38e138c0,0x379e36fc,0x39213901,0x386b381e,0x395e3940,0x38fe38b6,0x399a397c,0x39883944,0x39d339b7,0x3a0539c8,0x3a0a39ef,0x3a773a40,0x3a3e3a24,0x3adc3aab,0x3a703a57,0x3b333b09,
0x3a703a8b,0x3b1c3b47,0x3a363a53,0x3abb3aed,0x39f93a18,0x3a4a3a84,0x39b939d9,0x39ca3a0c,0x39753997,0x393d3985,0x392f3953,0x38a438f2,0x38e6390b,0x38003854,0x389a38c0,0x36a73756,
0xb70db651,0xb4aeb309,0xb83cb7c5,0xb6ebb5d1,0xb8e6b892,0xb880b7fb,0xb983b936,0xb971b8fc,0xba12b9cc,0xba42b9de,0xba91ba53,0xbaefba9d,0xbafebaca,0xbb74bb37,0xbb5abb2e,0xbbcebba6,
0xbb40bb6c,0xbbb2bbd8,0xbad9bb0f,0xbb43bb80,0xba5dba9d,0xbaa6bafa,0xb9cfba18,0xb9e0ba48,0xb92fb981,0xb8f5b96e,0xb880b8d9,0xb7d5b873,0xb788b824,0xb590b6b8,0xb5fab6c3,0xb251b460,
0x367935a2,0x34113197,0x380b374b,0x3684354f,0x38cd386e,0x386637af,0x397e3928,0x396c38ed,0x3a1e39d1,0x3a4e39e2,0x3aa93a66,0x3b043aaf,0x3b1f3ae7,0x3b8c3b4e,0x3b7d3b51,0x3be03bbd,
0x3b613b8d,0x3bc73be8,0x3af53b2e,0x3b5a3b97,0x3a703ab6,0x3ab73b0f,0x39d33a24,0x39e43a53,0x3921397c,0x38e6396a,0x385c38c0,0x37883859,0x370d37e6,0x350e3651,0x3549362e,0x30de3383,
0xb5e2b4f0,0xb2e4b023,0xb7b4b6cf,0xb61db4cc,0xb8b4b849,0xb84cb761,0xb97ab919,0xb967b8de,0xba2ab9d5,0xba59b9e6,0xbac1ba79,0xbb19bac0,0xbb3dbb03,0xbba2bb65,0xbb9cbb70,0xbbefbbd0,
0xbb7fbbaa,0xbbd8bbf4,0xbb10bb4c,0xbb6fbbac,0xba82bacd,0xbac8bb23,0xb9d7ba30,0xb9e8ba5f,0xb912b978,0xb8d7b965,0xb836b8a7,0xb73ab83e,0xb690b783,0xb48ab5e8,0xb496b596,0xaecfb244,
0x3549343b,0x31a42d58,0x37503651,0x35b33447,0x389a3824,0x38313713,0x3975390b,0x396338cf,0x3a3639d9,0x3a6539ea,0x3ad93a8b,0x3b2d3ad0,0x3b5a3b1d,0x3bb53b7a,0x3bb73b8d,0x3bf93be0,
0x3b9a3bc3,0x3be73bfc,0x3b2a3b67,0x3b833bbe,0x3a943ae4,0x3ad93b37,0x39db3a3c,0x39ec3a6a,0x39033973,0x38c83961,0x3811388d,0x36eb3824,0x3611371e,0x3405357e,0x33c034fc,0x2bc03103,
0xb061a8cf,0x25b230ac,0xb549b383,0xb32eae84,0xb816b6c3,0xb750b57e,0xb95eb8c0,0xb94bb883,0xba70b9ef,0xba9bb9ff,0xbb40bae1,0xbb83bb1d,0xbbc7bb8d,0xbbf5bbcc,0xbbffbbed,0xbbeabbff,
0xbbf2bc00,0xbbfebbe3,0xbb96bbcf,0xbbd2bbf9,0xbae9bb49,0xbb25bb8b,0xb9f1ba75,0xba01baa1,0xb8b9b95c,0xb87bb949,0xb69bb809,0xb555b734,0xb2fdb514,0xad71b2bf,0xa376af7e,0x31662966,
0x2e39a052,0xabf2b21f,0x34de3276,0x32512c5e,0x37f63673,0x3718352c,0x395a38b1,0x39473873,0x3a7b39f3,0x3aa63a03,0x3b523af0,0x3b923b2c,0x3bd63b9f,0x3bfb3bd8,0x3c003bf6,0x3bda3bfc,
0x3bfa3bff,0x3bf93bd1,0x3ba73bdd,0x3bdd3bfd,0x3af83b5b,0x3b333b99,0x39f53a80,0x3a053aab,0x38a93957,0x386b3944,0x364b37db,0x350236fc,0x31ee34a8,0x2a9331e2,0xa8062cf4,0xb2d8ad3f,
0xab5c2af8,0x2e843390,0xb472b166,0xb172a86b,0xb7bfb622,0xb6e0b4d8,0xb955b8a2,0xb942b863,0xba86b9f7,0xbab0ba08,0xbb64bb00,0xbba0bb39,0xbbe3bbaf,0xbbffbbe2,0xbbfdbbfd,0xbbc6bbf5,
0xbbffbbfa,0xbbf1bbba,0xbbb7bbe8,0xbbe7bc00,0xbb07bb6c,0xbb40bba6,0xb9f9ba8b,0xba0abab6,0xb89ab953,0xb85cb940,0xb5fab7a4,0xb4aeb6c3,0xb0deb43b,0xa484b103,0x2cf4a8cf,0x34232fc9,
0x2484ae6b,0xb086b47e,0x34053055,0x30931248,0x378835d1,0x36a73484,0x39503892,0x393d3854,0x3a9139fb,0x3abb3a0c,0x3b743b0f,0x3bad3b47,0x3bed3bbe,0x3c003beb,0x3bf63c00,0x3bae3beb,
0x3c003bf0,0x3be53ba0,0x3bc53bf2,0x3bef3c00,0x3b163b7c,0x3b4d3bb3,0x39fd3a96,0x3a0e3ac0,0x388b394e,0x384c393b,0x35a8376c,0x345a368a,0x2f97339c,0xa4203023,0xafe298b6,0xb4d8b128,
0x31c93531,0x355b37e0,0xaf652839,0x9d7f315a,0xb66db42f,0xb584b1b0,0xb939b844,0xb925b803,0xbac5ba10,0xbaecba20,0xbbb9bb53,0xbbdfbb82,0xbbffbbf2,0xbbe3bc00,0xbb91bbde,0xbaf7bb8a,
0xbbd6bb81,0xbb7cbadf,0xbbf5bbfd,0xbc00bbdd,0xbb5abbbe,0xbb88bbe3,0xba12baca,0xba22baf0,0xb83cb936,0xb7f6b923,0xb405b651,0xb15ab567,0x2a61ae84,0x31e22052,0x358a3269,0x381935a8,
0xb309b5e2,0xb5f4b841,0x2da3ac44,0xa5b2b269,0x363433b4,0x35493103,0x39343834,0x392137e6,0x3acf3a14,0x3af53a24,0x3bc43b60,0x3be73b8d,0x3bfb3bf8,0x3bd63bff,0x3b703bce,0x3ac63b6d,
0x3bc53b5f,0x3b5d3aad,0x3bfa3bf9,0x3bff3bcf,0x3b663bc9,0x3b923bea,0x3a163ad4,0x3a263afa,0x382c3931,0x37d5391e,0x335f3617,0x30ac352c,0xad582cc2,0xb2f0a89d,0xb63ab3a8,0xb869b63f,
0x34233690,0x368a3890,0xabc02e6b,0x2a613377,0xb5fab309,0xb50eb055,0xb92fb824,0xb91cb7c5,0xbad9ba18,0xbafeba28,0xbbcebb6c,0xbbedbb97,0xbbf6bbfc,0xbbc7bbfd,0xbb4cbbba,0xba93bb4d,
0xbbafbb38,0xbb3cba77,0xbbfebbf2,0xbbfcbbbf,0xbb72bbd3,0xbb9cbbf0,0xba1abadd,0xba2abb03,0xb81cb92d,0xb7b4b919,0xb2b3b5dc,0xaffbb4f0,0x2f7ea9fd,0x33fd2c12,0x36e53472,0x38b636d4,
0xb4c0b73a,0xb71eb8dc,0x2839b048,0xacf4b441,0x35bf325d,0x34d22f4c,0x392a3813,0x391737a4,0x3ae23a1c,0x3b073a2c,0x3bd73b77,0x3bf33ba1,0x3bee3bff,0x3bb63bfa,0x3b233ba4,0x3a5b3b2a,
0x3b973b0d,0x3b183a3e,0x3c003be9,0x3bf73bad,0x3b7d3bdb,0x3ba63bf5,0x3a1e3ae7,0x3a2e3b0c,0x380b3928,0x37933914,0x320735a2,0x2e9d34b4,0xb0d124e9,0xb484add5,0xb78eb50e,0xb901b767,
0xb97239ba,0x39dc3996,0xb8323ab5,0x3ad0385d,0x3927b9fe,0xba1fb94d,0x37b7bae9,0xbb02b807,0xb8d83a3f,0x3a5e3900,0xb7053b1a,0x3b30375e,0x3887ba7c,0xba99b8b0,0x364ebb46,0xbb5ab6aa,
0xb90039dc,0x3a3f3972,0xad7e3be6,0x3bf83115,0x3807ba99,0xbae9b887,0xabd9bc00,0xbbfca248,0xb5f13b30,0x3b6e3705,0x32a13bed,0x3bd4b04e,0x3365bba0,0xbbc9b4d5,0xb593bbaf,0xbb803475,
0xb88739fe,0x3a99394d,0x35f13bbc,0x3b6eb414,0x3593bb1a,0xbb80b75e,0xb8b0bb02,0xba7c37b7,0xaf0e3bc9,0x3bf43365,0x3a1f39dc,0x3927b972,0xb04ebc00,0xbbed2248,0xbb30b85d,0xb7053ab5,
0xb8073a1f,0x3ae93927,0x39fe3a3f,0x394db900,0x31dbbb80,0xbbddb593,0xbb6eb832,0xb5f13ad0,0x31153c00,0x3be62248,0x3bff32a1,0x28b6bbd4,0xb7b7bb91,0xbb023534,0xbba0304e,0x34d53bed,
0xb7053a3f,0x3b303900,0x3bbc375e,0x3414bb1a,0x2248bbc9,0xbc00b365,0xbbdda8b6,0x31db3bff,0x36aa3bd4,0x3b46b2a1,0x3a7cb64e,0xb8b0bb5a,0xba1fba5e,0xb92738d8,0xb7b739fe,0x3b02394d,
0xb5f13a5e,0x3b6e38d8,0x3bd42bd9,0xb2a1bbfc,0xb115bbf4,0xbbe6af0e,0xb9dc375e,0x39723b1a,0x39273b46,0x3a1fb6aa,0x3475bad0,0xbbafb832,0xbb91b887,0xb5343a99,0x34143c00,0x3bbc2248,
0xb4d53a7c,0x3ba038b0,0x3a3fb593,0xb900bb80,0xb534bc00,0xbb912248,0xb4143ab5,0x3bbc385d,0x3a993a5e,0x3887b8d8,0xb5f1bbfc,0xbb6e2bd9,0xbbffb475,0x28b63baf,0x3ad03a1f,0x3832b927,
0xb3653a99,0x3bc93887,0x36aab996,0xbb46b9ba,0xb7b7bbed,0xbb02304e,0x34d53bfc,0x3ba02bd9,0x3b913927,0x3534ba1f,0xbae9ba3f,0xb8073900,0xbb5a28b6,0x364e3bff,0x3bd43115,0xb2a1bbe6,
0xb1153ab5,0x3be6385d,0xa8b6bb6e,0xbbffb5f1,0xb900bbbc,0xba3f3414,0x3a1f3b30,0x3927b705,0x3bfc375e,0x2bd9bb1a,0xbbedb475,0x304e3baf,0xb9ba3593,0x39963b80,0x3887b832,0xba99bad0,
0xad7e3ad0,0x3bf83832,0xb7b7bbff,0xbb0228b6,0xb9febb6e,0xb94d35f1,0x3bed3887,0x304eba99,0x3bd43414,0xb2a1bbbc,0xb9963534,0x39ba3b91,0xb6aa3900,0x3b463a3f,0xb115bba0,0xbbe6b4d5,
0xa2483ae9,0x3c003807,0xba99bb30,0xb8873705,0xbad0bb02,0xb83237b7,0x3b462d7e,0xb6aabbf8,0x3b1a28b6,0xb75ebbff,0xaf0e3a7c,0x3bf438b0,0xabd93ab5,0x3bfc385d,0xba5ebb5a,0xb8d8364e,
0x2bd93b02,0x3bfc37b7,0xbbedb927,0xb04e3a1f,0xbb6eba7c,0xb5f138b0,0x385db6aa,0xbab5bb46,0x39dcb1db,0xb972bbdd,0x38323c00,0x3ad02248,0x34d53bbc,0x3ba03414,0xbbf4b705,0x2f0e3b30,
0x304e3b1a,0x3bed375e,0xbb91b475,0x35343baf,0xbbd4b9dc,0xb2a13972,0x2248ba7c,0xbc00b8b0,0x3832b64e,0xbad0bb5a,0x3b803a99,0x3593b887,0x39003bfc,0x3a3fabd9,0xb9273414,0x3a1f3bbc,
0x32a13b30,0x3bd43705,0xb996304e,0x39ba3bed,0xbbffb927,0xa8b63a1f,0xb832bbf4,0xbad0af0e,0x3475b8b0,0xbbafba7c,0x3ba03593,0xb4d5bb80,0x3ae93b6e,0x3807b5f1,0x2bd93a99,0x3bfc3887,
0x34753b46,0x3baf36aa,0xb4d53832,0x3ba03ad0,0xbbedb85d,0x304e3ab5,0xbb30bb5a,0xb705364e,0x2248b9fe,0xbc00b94d,0x3887b414,0xba99bbbc,0x3be63a1f,0x3115b927,0x39dc3bf4,0x3972af0e,
0x35933b5a,0x3b80364e,0x31153a99,0x3be63887,0xbba0b705,0x34d53b30,0xbbf4b8d8,0x2f0e3a5e,0xb414bb02,0xbbbcb7b7,0xabd9ba1f,0xbbfcb927,0x3bd43832,0xb2a1bad0,0x3c003972,0xa248b9dc,
0x36aa3b6e,0x3b4635f1,0x38b03bdd,0x3a7c31db,0xbb1ab534,0x375e3b91,0xba3fb04e,0x39003bed,0xb807bbaf,0xbae9b475,0xb94dbbf8,0xb9fead7e,0x3ab53365,0xb85dbbc9,0x39ba28b6,0xb996bbff,
0x37b73b80,0x3b023593,0x3b1a3bc9,0x375eb365,0xba5eb2a1,0x38d83bd4,0xb53435f1,0x3b913b6e,0xb9babbfc,0xb996abd9,0xbbddbae9,0xb1db3807,0x38b0ad7e,0xba7cbbf8,0x28b6b900,0xbbffba3f,
0x385d3b91,0x3ab53534,0x3c003a5e,0x2248b8d8,0xb972ad7e,0x39dc3bf8,0x33653a3f,0x3bc93900,0xbb02bbe6,0xb7b73115,0xbb1ab6aa,0x375e3b46,0x3414b64e,0xbbbcbb5a,0xb94dbbdd,0xb9feb1db,
0x38d83ba0,0x3a5e34d5,0x3b3037b7,0xb705bb02,0xb85d28b6,0x3ab53bff,0x39ba3be6,0x39963115,0xbbc9bb6e,0xb36535f1,0xb6aa31db,0x3b463bdd,0xaf0eb94d,0xbbf4b9fe,0xbbf8bae9,0xad7e3807,
0x394d3baf,0x39fe3475,0x38d82d7e,0xba5ebbf8,0xb64e3115,0x3b5a3be6,0x3bd43b80,0x32a1b593,0xbbffba99,0x28b63887,0x336539ba,0x3bc93996,0xb75ebae9,0xbb1ab807,0xba3fb534,0x39003b91,
0x39ba3bbc,0x39963414,0x31dbb534,0xbbddbb91,0xb3653475,0x3bc93baf,0x3b803927,0xb593ba1f,0xbba0b972,0x34d539dc,0x3a3f3be6,0x39003115,0xb9febbd4,0xb94db2a1,0xb04e35f1,0x3bed3b6e,
0x3a1f3bc9,0x39273365,0xb475b972,0xbbafb9dc,0xabd9364e,0x3bfc3b5a,0x38d831db,0xba5ebbdd,0xbab5b807,0x385d3ae9,0x3c003b30,0x2248b705,0xbb80bbf4,0xb5932f0e,0x38b03b1a,0x3a7c375e,
0x3a7c3bd4,0x38b032a1,0xb972bb5a,0xb9dcb64e,0x2f0e3807,0x3bf43ae9,0x2d7eb534,0xbbf8bb91,0xb94db4d5,0x39fe3ba0,0x3a5e37b7,0xb8d8bb02,0xbc00bb46,0x224836aa,0x3bdd3bc9,0x31dbb365,
0x3ad03bdd,0x383231db,0xbb80bc00,0xb5932248,0x347538d8,0x3baf3a5e,0xb75eb9fe,0xbb1ab94d,0xb705ad7e,0x3b303bf8,0x3414af0e,0xbbbcbbf4,0xbb6eb9dc,0x35f13972,0x3ab538b0,0xb85dba7c,
0x3b1a3be6,0x375e3115,0xbbf4bb46,0x2f0e36aa,0x37053996,0x3b3039ba,0xbae9bbd4,0xb807b2a1,0xb1db304e,0x3bdd3bed,0xb64eb94d,0xbb5ab9fe,0xb9dcb7b7,0x39723b02,0x3365ad7e,0xbbc9bbf8,
0x3b5a3bed,0x364e304e,0xbab5b94d,0x385d39fe,0x38b03a3f,0x3a7c3900,0xbbffbba0,0x28b634d5,0x2d7e3593,0x3bf83b80,0xbb02bbc9,0xb7b7b365,0xb705b1db,0x3b303bdd,0xb807b9ba,0xbae9b996,
0x3b913bf4,0x35342f0e,0xb807b4d5,0x3ae93ba0,0x39ba3ad0,0x39963832,0xba99b972,0x388739dc,0x3593385d,0x3b803ab5,0xbbe6bb6e,0x311535f1,0xad7e304e,0x3bf83bed,0xbbafbbfc,0xb475abd9,
0x3bbc3bf8,0x34142d7e,0xabd92f0e,0x3bfc3bf4,0x3a993b46,0x388736aa,0xb64eb365,0x3b5a3bc9,0x38b039ba,0x3a7c3996,0xb972b85d,0x39dc3ab5,0x34753705,0x3baf3b30,0xbb1aba5e,0x375e38d8,
0x3bdd3bfc,0x31db2bd9,0x364e3807,0x3b5a3ae9,0x3b463ba0,0x36aa34d5,0x31153475,0x3be63baf,0x3a3f3ad0,0x39003832,0xad7e28b6,0x3bf83bff,0x38d83996,0x3a5e39ba,0xb534b2a1,0x3b913bd4,
0x3bf43bff,0x2f0e28b6,0x3a1f3a7c,0x392738b0,0x3bbc3bdd,0x341431db,0x394d39ba,0x39fe3996,0x3b5a3b91,0x364e3534,0x385d38d8,0x3ab53a5e,0x3ad03b1a,0x3832375e,0x36aa37b7,0x3b463b02,
0x3bff3c00,0x28b62248,0x3bc93bd4,0x336532a1,0x3bf83bfc,0x2d7e2bd9,0x3baf3bbc,0x34753414,0x3bed3bf4,0x304e2f0e,0x3b913ba0,0x353434d5,0x3bdd3be6,0x31db3115,0x3b6e3b80,0x35f13593,
0xb5933b6e,0x3b8035f1,0xb1153bdd,0x3be631db,0x34d5bb91,0xbba0b534,0x2f0ebbed,0xbbf4b04e,0xb4143baf,0x3bbc3475,0xabd93bf8,0x3bfc2d7e,0x32a1bbc9,0xbbd4b365,0x2248bbff,0xbc00a8b6,
0x37b73b46,0x3b02b6aa,0x3b1a3832,0x375ebad0,0xb8d8bab5,0xba5e385d,0xbb91b64e,0xb5343b5a,0x39ba39fe,0x3996b94d,0x3bdd3414,0x31dbbbbc,0xba7cb927,0xb8b03a1f,0xbbffaf0e,0xa8b63bf4,
0x3bd43534,0x32a1bb91,0x39bab8d8,0xb996ba5e,0xbbffad7e,0x28b63bf8,0xb8323a3f,0x3ad03900,0x3bafb115,0xb475bbe6,0x34d5bb46,0xbba0b6aa,0xbae9364e,0x38073b5a,0xabd93bdd,0x3bfc31db,
0x3a5eb75e,0xb8d8bb1a,0xb705bbaf,0xbb303475,0xb85d39dc,0x3ab53972,0x39ba3a7c,0x3996b8b0,0x3365bb5a,0xbbc9b64e,0xbb46b887,0xb6aa3a99,0x2f0e3bfc,0x3bf42bd9,0x3bf83414,0x2d7ebbbc,
0x2bd9bbaf,0xbbfcb475,0xbbedad7e,0x304e3bf8,0x35f13be6,0x3b6eb115,0x3ab5b593,0xb85dbb80,0xb9dcba99,0xb9723887,0xb83239ba,0x3ad03996,0x3ba03807,0x34d5bae9,0x2f0ebb91,0xbbf4b534,
0xb9babae9,0xb9963807,0xb1db3b30,0x3bdd3705,0x3bc937b7,0x3365bb02,0xb593bbf8,0xbb802d7e,0xbba028b6,0x34d53bff,0x3a3f3a7c,0x3900b8b0,0x394db85d,0xb9febab5,0xbbedb64e,0xb04e3b5a,
0xbbf8b365,0x2d7e3bc9,0x3b0239dc,0x37b7b972,0x39feb64e,0xb94dbb5a,0xbbedb1db,0x304e3bdd,0xb2a13ae9,0x3bd43807,0x39bab705,0xb996bb30,0xb6aabbf4,0xbb462f0e,0xb1153b1a,0x3be6375e,
0xb8b0385d,0x3a7c3ab5,0x39dcb5f1,0xb972bb6e,0xaf0ebbbc,0xbbf4b414,0xad7e3b30,0x3bf83705,0x39fe3b1a,0x394db75e,0xb8d8bbaf,0xba5e3475,0xbc00b593,0x22483b80,0x3bdd3832,0x31dbbad0,
0x33653bdd,0x3bc931db,0xb6aabc00,0xbb462248,0xbb02ba5e,0xb7b738d8,0x3ba0394d,0x34d5b9fe,0x3b912d7e,0xb534bbf8,0xbae92f0e,0x38073bf4,0xb64e3972,0x3b5a39dc,0x32a1ba7c,0xbbd4b8b0,
0x3b1a3a7c,0x375eb8b0,0xbbf4b593,0x2f0e3b80,0xbb30a248,0x37053c00,0x3807b85d,0xbae9bab5,0x31dbba5e,0xbbddb8d8,0x364e3bfc,0x3b5a2bd9,0x39723baf,0x39dcb475,0xbbc9b927,0xb3653a1f,
0x3b6e304e,0xb5f1bbed,0xb2a139fe,0x3bd4394d,0xb1153a3f,0x3be63900,0xb9dcbba0,0xb97234d5,0xba1fbb80,0xb9273593,0x3baf3365,0xb475bbc9,0x3b9131db,0xb534bbdd,0xb41439ba,0x3bbc3996,
0x3534b900,0xbb91ba3f,0x3ae93b1a,0x3807b75e,0x39ba3bc9,0x3996b365,0xba9928b6,0x38873bff,0xbb80b2a1,0x35933bd4,0xb115bb5a,0xbbe6b64e,0x2d7eba5e,0xbbf8b8d8,0x3baf39fe,0x3475b94d,
0xb807bbf8,0xbae9ad7e,0x39feaf0e,0xb94dbbf4,0x3bdd36aa,0xb1dbbb46,0x35f13bc9,0x3b6e3365,0xb11539ba,0x3be63996,0xbbffb85d,0x28b63ab5,0xbb02bb30,0xb7b73705,0x34d5b8d8,0xbba0ba5e,
0xbbddb9fe,0xb1db394d,0xb64ebbbc,0xbb5ab414,0x36aab75e,0xbb46bb1a,0x3be637b7,0xb115bb02,0x3a3f3bc9,0x3900b365,0xad7e39dc,0x3bf83972,0xba5ea248,0x38d83c00,0xbb91bab5,0xb534385d,
0xba3fa8b6,0x39003bff,0xbbf8b8b0,0x2d7e3a7c,0xb807bbdd,0xbae9b1db,0x2bd9b9ba,0xbbfcb996,0x3b6e3534,0xb5f1bb91,0x3bd43a5e,0x32a1b8d8,0x33653b1a,0x3bc9375e,0xb59337b7,0x3b803b02,
0xa8b63996,0x3bff39ba,0xb365385d,0x3bc93ab5,0xbbf8b9fe,0xad7e394d,0xbbafbae9,0xb4753807,0x304eb900,0xbbedba3f,0x3534b75e,0xbb91bb1a,0x3bdd3a7c,0x31dbb8b0,0x3b6e3b46,0x35f1b6aa,
0x39dc3c00,0x3972a248,0x3ad03bd4,0x3832b2a1,0xb9272bd9,0x3a1f3bfc,0xb7b73414,0x3b023bbc,0xba5ebbf4,0xb8d82f0e,0xbb30bba0,0xb70534d5,0x3887b115,0xba99bbe6,0x364eb593,0xbb5abb80,
0x3bf43972,0xaf0eb9dc,0x3a1f3115,0xb927bbe6,0x34143a99,0x3bbc3887,0x39fe3c00,0x394d2248,0xbb5ab705,0x364e3b30,0xb85d304e,0x3ab53bed,0xb832bba0,0xbad0b4d5,0xbb46bbaf,0xb6aa3475,
0x3887abd9,0xba99bbfc,0xb5f1bae9,0xbb6eb807,0x3b803ba0,0x3593b4d5,0x3a7c3475,0xb8b0bbaf,0xaf0e3832,0x3bf43ad0,0x3a1f3bff,0x392728b6,0xbbedb996,0x304e39ba,0xb70532a1,0x3b303bd4,
0xb414ba1f,0xbbbcb927,0xbbfcba3f,0x2bd93900,0x3a993593,0xb887bb80,0xb64ebad0,0xbb5ab832,0x3a7c3c00,0x38b02248,0x39dc32a1,0xb972bbd4,0xb4753534,0x3baf3b91,0x3b1a3bed,0x375eb04e,
0xbb30bbf4,0xb7052f0e,0xb41434d5,0x3bbc3ba0,0x2248b832,0xbc00bad0,0xbbddb9dc,0x31db3972,0x3b46385d,0xb6aabab5,0xb8b0bb6e,0xba7cb5f1,0x3a1f3bed,0x3927304e,0x37b7abd9,0xbb02bbfc,
0xbb5ab8d8,0x364e3a5e,0x3ab53bfc,0x385d2bd9,0xba7cbbf4,0xb8b0af0e,0xa8b6375e,0x3bff3b1a,0x2d7eb6aa,0xbbf8bb46,0xbb02b832,0x37b73ad0,0x3b303887,0xb705ba99,0xbae9bc00,0xb807a248,
0xb4d53115,0x3ba03be6,0x3a3f36aa,0xb900bb46,0xbb91b996,0x353439ba,0x3bbc3bd4,0x3414b2a1,0xba99bbed,0xb887b04e,0x35f139fe,0x3b6e394d,0xa8b6b7b7,0xbbffbb02,0xb832ad7e,0x3ad03bf8,
0x38323a99,0x3ad03887,0xb593b996,0xbb80b9ba,0xb475304e,0x3baf3bed,0x375e2bd9,0xbb1abbfc,0xbb30b927,0x37053a1f,0x3bbc3a3f,0xb414b900,0xbb6ebbff,0xb5f128b6,0x3ab53be6,0x385d3115,
0x3be63bd4,0x3115b2a1,0xbbffbb5a,0x28b6364e,0x39003ae9,0x3a3f3807,0xba1fbb91,0xb927b534,0xabd934d5,0x3bfc3ba0,0xb04eb7b7,0xbbedbb02,0xb9bab6aa,0x39963b46,0x38873365,0xba99bbc9,
0x3a1f3832,0xb927bad0,0xb47528b6,0x3baf3bff,0x3bfc3b6e,0xabd9b5f1,0xba5eb887,0x38d83a99,0x3ab53bbc,0x385d3414,0xbc00bb91,0x22483534,0x35933900,0x3b803a3f,0xba7cbba0,0xb8b0b4d5,
0x2248b414,0xbc00bbbc,0x3a993b91,0x38873534,0x38323475,0xbad0bbaf,0x36aa3927,0x3b463a1f,0x3b1a39dc,0xb75eb972,0xaf0e3115,0x3bf43be6,0x3bfc3bd4,0x2bd9b2a1,0xb8d8b5f1,0x3a5e3b6e,
0xb9febb02,0xb94db7b7,0x3a5e3927,0xb8d8ba1f,0xb64eb8b0,0xbb5aba7c,0x3bd43b46,0xb2a1b6aa,0x28b6b1db,0xbbffbbdd,0x3bc93c00,0x33652248,0x375e3414,0xbb1abbbc,0x3a3f3b30,0x39003705,
0xbbedbba0,0x304e34d5,0xb534b7b7,0xbb91bb02,0xbbd4bbff,0xb2a1a8b6,0x2248b115,0xbc00bbe6,0xbad0bb6e,0xb832b5f1,0x359331db,0xbb80bbdd,0xb900b9fe,0xba3fb94d,0x39273807,0xba1fbae9,
0xb85db705,0x3ab53b30,0xbc00bbed,0x2248304e,0xb9dcb927,0x39723a1f,0xbbc9bbf4,0xb365af0e,0xbb02ba7c,0x37b738b0,0xbb1abb80,0xb75eb593,0xbbbcbb6e,0x341435f1,0xb9feba99,0xb94db887,
0x34753593,0x3baf3b80,0xb4d5b365,0x3ba03bc9,0x304e32a1,0x3bed3bd4,0xb705b5f1,0x3b303b6e,0xa2482bd9,0x3c003bfc,0xb887b807,0x3a993ae9,0xb115ad7e,0x3be63bf8,0xb972b900,0x39dc3a3f,
0x3b463b5a,0x36aa364e,0x3a7c3a99,0x38b03887,0x3b1a3b30,0x375e3705,0x3a3f3a5e,0x390038d8,0x3ae93b02,0x380737b7,0x39fe3a1f,0x394d3927,0x3ab53ad0,0x385d3832,0x39ba39dc,0x39963972,
0x28b63c00,0x3bffa248,0x33653bd4,0x3bc9b2a1,0xad7ebbfc,0xbbf82bd9,0xb475bbbc,0xbbaf3414,0x304e3bf4,0x3bedaf0e,0x35343ba0,0x3b91b4d5,0xb1dbbbe6,0xbbdd3115,0xb5f1bb80,0xbb6e3593,
0x3bf4a8b6,0xaf0ebbff,0x3a1fb8b0,0xb927ba7c,0xbbbc31db,0x34143bdd,0xb94d3996,0x39fe39ba,0x3b5ab534,0xb64ebb91,0x385dba5e,0xbab5b8d8,0xbad0375e,0x38323b1a,0xb6aa3b02,0x3b4637b7,
0xb1dbbbfc,0xbbdd2bd9,0xbb5ab807,0xb64e3ae9,0x36aa3ba0,0x3b46b4d5,0x3be63475,0x3115bbaf,0xb900bad0,0xba3f3832,0xbbf8a8b6,0x2d7e3bff,0x3a5e3996,0x38d8b9ba,0x3b91b2a1,0xb534bbd4,
0xbbbc2d7e,0x34143bf8,0x2bd93bf4,0x3bfc2f0e,0x3a99b6aa,0xb887bb46,0xb64ebbc9,0xbb5a3365,0xb8b03996,0x3a7c39ba,0x39723ab5,0x39dcb85d,0x3475bb30,0xbbafb705,0xbb1ab8d8,0xb75e3a5e,
0x35343bf4,0x3b91af0e,0x3ae9b4d5,0xb807bba0,0xb996bad0,0xb9ba3832,0xb8873972,0x3a9939dc,0x3b80385d,0x3593bab5,0x3115bb6e,0xbbe6b5f1,0xbbf8b04e,0x2d7e3bed,0x34753bfc,0x3bafabd9,
0x3b5ab04e,0xb64ebbed,0xbab5b9fe,0xb85d394d,0xb8b03900,0x3a7c3a3f,0x3bff34d5,0x28b6bba0,0x2d7ebb80,0xbbf8b593,0xbb023365,0x37b73bc9,0x37053bdd,0x3b30b1db,0x3807b996,0xbae9b9ba,
0xb75ebbe6,0xbb1a3115,0xaf0e3b46,0x3bf436aa,0x3b303996,0x3705b9ba,0xb807bbd4,0xbae932a1,0xbbddb04e,0x31db3bed,0x3b5a394d,0x364eb9fe,0x3972b7b7,0xb9dcbb02,0xbbc9ad7e,0x33653bf8,
0xbad031db,0x38323bdd,0x3b802248,0xb593bc00,0x3475ba5e,0xbbafb8d8,0xb75e394d,0x3b1a39fe,0x37053bf8,0x3b30ad7e,0xb414bbf4,0xbbbcaf0e,0xbb6eb972,0xb5f139dc,0x3ab53a7c,0x385db8b0,
0x38b03bd4,0x3a7cb2a1,0xb9dcbb5a,0xb972364e,0xbbf4b807,0xaf0e3ae9,0x3bf83534,0xad7ebb91,0x39feb4d5,0xb94dbba0,0xb8d837b7,0x3a5e3b02,0xa2483b46,0x3c0036aa,0xb1dbbbc9,0xbbddb365,
0x3a1fb365,0xb927bbc9,0xb47539dc,0x3baf3972,0x2bd93b5a,0x3bfc364e,0xb8d8bbdd,0xba5e31db,0xbab5bae9,0xb85d3807,0x3c003705,0xa248bb30,0x3b802f0e,0xb593bbf4,0xb8b0375e,0x3a7c3b1a,
0xb996bbbc,0xb9ba3414,0x3bdd3534,0xb1dbbb91,0x3bc93475,0xb365bbaf,0xb5933927,0x3b803a1f,0xb4d53972,0x3ba039dc,0xb900bbe6,0xba3f3115,0xb94dbbd4,0xb9fe32a1,0x3bed35f1,0xb04ebb6e,
0xb94d3475,0x39fe3baf,0xb8d8bbf8,0xba5e2d7e,0xb64ebbe6,0xbb5ab115,0x3bd43593,0xb2a1bb80,0x3bff3887,0x28b6ba99,0xb3653996,0x3bc939ba,0xb75e3807,0x3b1a3ae9,0xba3fbb91,0xb9003534,
0x3a5e3ba0,0x38d8b4d5,0xb70537b7,0x3b303b02,0xbab5a8b6,0x385d3bff,0xb996bbe6,0xb9ba3115,0xb365bb6e,0xbbc9b5f1,0x3b4631db,0xb6aabbdd,0x3bf4394d,0x2f0eb9fe,0x2d7e3ae9,0x3bf83807,
0x385db534,0xbab5bb91,0x3c0038d8,0xa248ba5e,0x39723bf8,0x39dcad7e,0xb3653900,0x3bc93a3f,0xbb02b115,0x37b73be6,0xbb1abb46,0xb75e36aa,0xb414bb5a,0xbbbcb64e,0x394db1db,0xb9febbdd,
0xbb02bb80,0xb7b73593,0xb75ebbc9,0xbb1ab365,0x38d8b2a1,0xba5ebbd4,0x3b9135f1,0xb534bb6e,0x39963bfc,0x39baabd9,0x31db3ae9,0x3bdd3807,0xba7cad7e,0x38b03bf8,0xbbffb900,0x28b63a3f,
0xb6aa35f1,0x3b463b6e,0xb8b031db,0x3a7c3bdd,0xbb1abb91,0xb75e3534,0xba3fbbed,0xb900304e,0x3807b475,0xbae9bbaf,0x394dad7e,0xb9febbf8,0x3ab53bc9,0x385db365,0x39ba3bff,0x3996a8b6,
0x3b803b5a,0x3593b64e,0x3be63a99,0x3115b887,0xb4d53705,0x3ba03b30,0xaf0e38d8,0x3bf43a5e,0xbbbcbb02,0xb41437b7,0xbbfcba1f,0xabd93927,0x32a1b832,0xbbd4bad0,0x2248b972,0xbc00b9dc,
0x3475b6aa,0xbbafbb46,0xb4d5bad0,0xbba0b832,0x3bed3ab5,0x304eb85d,0x3b30364e,0xb705bb5a,0x2248394d,0x3c0039fe,0x38873bbc,0x3a993414,0xbbe6b927,0x31153a1f,0xb9dcaf0e,0x39723bf4,
0xbbd4bb30,0xb2a13705,0xb9bab04e,0x39963bed,0xa8b6b927,0xbbffba1f,0xbad0bbf4,0xb8322f0e,0x3baf38b0,0xb475ba7c,0x34d5b593,0xbba0bb80,0x38073b6e,0x3ae935f1,0x3bfc3a99,0x2bd9b887,
0xb04e375e,0x3bed3b1a,0x3b913baf,0x3534b475,0xbbd4b972,0x32a139dc,0x224838b0,0x3c003a7c,0xb832bb5a,0xbad0b64e,0xbb80b887,0x35933a99,0x39002bd9,0xba3fbbfc,0xb927bbbc,0xba1fb414,
0x3bfc3b02,0x2bd9b7b7,0xb04eb927,0xbbedba1f,0x35f13a7c,0x3b6e38b0,0x3ab536aa,0xb85dbb46,0xb972b1db,0x39dc3bdd,0x3ad03c00,0x3832a248,0xbba0bbbc,0xb4d53414,0xaf0e3705,0x3bf43b30,
0xa248b807,0xbc00bae9,0xba99b705,0x38873b30,0x3ad037b7,0xb832bb02,0xbb46bbf8,0xb6aa2d7e,0x3b1a3bff,0x375ea8b6,0xaf0eb8b0,0xbbf4ba7c,0x2bd9385d,0x3bfc3ab5,0x3a5e364e,0xb8d8bb5a,
0xbbf8bad0,0x2d7e3832,0x3b023bff,0x37b728b6,0xb94dbb6e,0xb9feb5f1,0x304e3887,0x3bed3a99,0x32a1b414,0xbbd4bbbc,0xb9bab534,0x39963b91,0x3b463900,0xb6aaba3f,0xbbe6bba0,0xb11534d5,
0x3115385d,0x3be63ab5,0x28b6b5f1,0xbbffbb6e,0xb900b414,0x3a3f3bbc,0x3a1f3705,0xb927bb30,0xbbfcbb1a,0x2bd9375e,0x3bed3baf,0x304eb475,0xb9babb80,0xb996b593,0x38873ad0,0x3a993832,
0x3bc93a99,0xb365b887,0xbb46b996,0x36aa39ba,0x3b023bed,0x37b7304e,0xbba0bbfc,0xb4d52bd9,0x35343927,0x3b913a1f,0xb807ba3f,0xbae9b900,0xb64ea8b6,0x3b5a3bff,0x32a1b115,0xbbd4bbe6,
0xb4d5b8b0,0xbba0ba7c,0x3a3f3b80,0x39003593,0x35342248,0xbb91bc00,0x3414385d,0x3bbc3ab5,0x3a9938d8,0xb887ba5e,0xb5f1abd9,0x3b6e3bfc,0x3bff3baf,0x28b6b475,0xbad0b927,0x38323a1f,
0xbb6eba5e,0x35f138d8,0x32a1abd9,0xbbd4bbfc,0xbbe6bbf4,0xb1152f0e,0x3972375e,0xb9dcbb1a,0xba1fbb46,0xb927b6aa,0x3baf3ad0,0xb475b832,0xb534b887,0xbb91ba99,0x3bbc3c00,0x3414a248,
0x37053900,0x3b303a3f,0xbbbcbb1a,0x3414375e,0x22483365,0x3c003bc9,0xbbddbbff,0xb1db28b6,0xb6aab2a1,0x3b463bd4,0xba7cbb5a,0xb8b0b64e,0xba1fb8d8,0x39273a5e,0xb7b7b94d,0xbb02b9fe,
0x3ae93a1f,0xb807b927,0x394d3a3f,0x39fe3900,0x3bdd3b80,0xb1dbb593,0x35f13832,0x3b6e3ad0,0x3be63c00,0x3115a248,0x28b632a1,0x3bff3bd4,0x3b023b91,0x37b73534,0xb4d5b04e,0x3ba03bed,
0xb887b94d,0xba99b9fe,0x35f13414,0xbb6ebbbc,0xb593b75e,0xbb80bb1a,0x38b037b7,0xba7cbb02,0xaf0eb365,0xbbf4bbc9,0x3a1f3972,0xb927b9dc,0x304e2248,0xbbedbc00,0x3b303ab5,0xb705b85d,
0xba3fb9dc,0x39003972,0xbbf8bbe6,0x2d7e3115,0xbae9ba99,0x38073887,0xbbfcbc00,0xabd92248,0xbb6ebb30,0x35f13705,0xbbd4bbed,0xb2a1b04e,0xbbc9bba0,0x336534d5,0xbb80bbaf,0xb593b475,
0x39723996,0x39dc39ba,0x3832385d,0x3ad03ab5,0x3927394d,0x3a1f39fe,0x37b73807,0x3b023ae9,0x38d83900,0x3a5e3a3f,0x3705375e,0x3b303b1a,0x388738b0,0x3a993a7c,0x364e36aa,0x3b5a3b46,
0x36aa3b5a,0x3b46b64e,0x38b03a99,0x3a7cb887,0xb75ebb30,0xbb1a3705,0xb900ba5e,0xba3f38d8,0x38073b02,0x3ae9b7b7,0x394d3a1f,0x39feb927,0xb85dbad0,0xbab53832,0xb996b9dc,0xb9ba3972,
0x3475bb80,0xbbafb593,0xb4d5bbc9,0xbba03365,0xb04e3bd4,0x3bed32a1,0x37053b6e,0x3b30b5f1,0xa248bbfc,0xbc00abd9,0xb887bae9,0xba993807,0x31153bf8,0x3be6ad7e,0x39723a3f,0x39dcb900,
0xbab53705,0x385d3b30,0xa2483bed,0x3c00304e,0x3972b927,0xb9dcba1f,0xb365bbf4,0xbbc92f0e,0xb7b73a7c,0x3b0238b0,0x375e3b80,0x3b1ab593,0x3414bb6e,0xbbbcb5f1,0xb94dba99,0xb9fe3887,
0x3bed34d5,0x304ebba0,0x3534bb02,0xbb91b7b7,0xbbd428b6,0x32a13bff,0x22483be6,0x3c003115,0x3ad0b5f1,0xb832bb6e,0xb593bbdd,0xbb8031db,0xb900394d,0x3a3f39fe,0x39273ae9,0x3a1fb807,
0xb94dbb02,0xb9fe37b7,0xb8d83927,0x3a5e3a1f,0x3b5a38b0,0x364eba7c,0x32a1bb46,0xbbd4b6aa,0xbbffb1db,0x28b63bdd,0x33653c00,0x3bc9a248,0x3b1ab414,0xb75ebbbc,0xb900bb30,0xba3f3705,
0x22483bbc,0x3c003414,0x3a99b534,0xb887bb91,0xb832bbaf,0xbad03475,0xb6aa3a1f,0x3b463927,0x3b1a3972,0x375eb9dc,0xaf0ebbe6,0xbbf4b115,0xbbfcb2a1,0x2bd93bd4,0x38d83b6e,0x3a5eb5f1,
0x3927b832,0xba1fbad0,0xbbafa8b6,0x34753bff,0xabd93b6e,0x3bfc35f1,0x38d8b887,0xba5eba99,0xb85dbbbc,0xbab53414,0xa2483b91,0x3c003534,0x3b803900,0x3593ba3f,0xb8b0bba0,0xba7c34d5,
0xbbe6b2a1,0x31153bd4,0x3bff364e,0x28b6bb5a,0x3900b807,0xba3fbae9,0xba1f3534,0x39273b91,0x2bd93ba0,0x3bfc34d5,0x304ebb02,0xbbedb7b7,0xb9babb46,0xb99636aa,0x38873bc9,0x3a99b365,
0x3ad03a99,0x3832b887,0xbb80b996,0xb59339ba,0xbbafb04e,0x34753bed,0x3b1aabd9,0xb75ebbfc,0x3705b927,0xbb30ba1f,0xb4143a3f,0x3bbc3900,0x35f13bff,0x3b6e28b6,0xb85dbbe6,0xbab53115,
0xb4d5bbe6,0xbba0b115,0x3a3f3b46,0x3900b6aa,0x3b9139ba,0x3534b996,0xbbbcb2a1,0x34143bd4,0xba99304e,0x38873bed,0x35f1b94d,0xbb6eb9fe,0x28b6bb02,0xbbffb7b7,0x38323bf8,0x3ad0ad7e,
0xb64e38d8,0x3b5a3a5e,0xb85dbbfc,0xbab52bd9,0xb8b0bbf4,0xba7c2f0e,0x3bff375e,0xa8b6bb1a,0x3bf836aa,0xad7ebb46,0xb7b73832,0x3b023ad0,0xb7053887,0x3b303a99,0xb807bc00,0xbae92248,
0x3b302f0e,0xb705bbf4,0x34143ba0,0x3bbc34d5,0x22483ad0,0x3c003832,0xbbddb972,0xb1db39dc,0xbb46bab5,0xb6aa385d,0x38b0b5f1,0xba7cbb6e,0x3a1fb04e,0xb927bbed,0x37b73bfc,0x3b022bd9,
0xbbbcba1f,0xb4143927,0x2bd9ba3f,0xbbfcb900,0x3887b593,0xba99bb80,0x3b5a3ad0,0x364eb832,0x38b03c00,0x3a7ca248,0xb97232a1,0x39dc3bd4,0xbbafb534,0x34753b91,0xb75ebbed,0xbb1ab04e,
0x38873bfc,0x3a992bd9,0xb5f13807,0x3b6e3ae9,0xbb80b4d5,0x35933ba0,0xba7cbbaf,0xb8b03475,0xaf0ebad0,0xbbf4b832,0x3a1fa8b6,0xb927bbff,0x3bed39ba,0x304eb996,0x37053bd4,0x3b3032a1,
0x2f0eb972,0xbbf4b9dc,0x3927b115,0xba1fbbe6,0x3bbc3a99,0x3414b887,0x394d3c00,0x39fea248,0xb64e3705,0x3b5a3b30,0xbab5b04e,0x385d3bed,0xbad0bba0,0xb83234d5,0xb6aabbaf,0xbb46b475,
0xb9dca248,0x39723c00,0xbad0b2a1,0x38323bd4,0xb927bbfc,0xba1fabd9,0xb7b7bbbc,0xbb02b414,0x3a5e2f0e,0xb8d8bbf4,0x3b3034d5,0xb705bba0,0x38873be6,0x3a993115,0x364e3b80,0x3b5a3593,
0x3bff3996,0xa8b6b9ba,0x3bc9385d,0xb365bab5,0x2d7e39fe,0x3bf8394d,0x34753ae9,0x3baf3807,0xbbedb900,0x304e3a3f,0xbb91b75e,0x35343b1a,0xb1dbba7c,0xbbddb8b0,0xb5f1bb46,0xbb6eb6aa,
0xba3fbbff,0xb90028b6,0xbbf8ba7c,0xad7e38b0,0x3807b1db,0xbae9bbdd,0xabd9b996,0xbbfcb9ba,0x3b6e3b91,0x35f1b534,0x3bd438d8,0xb2a1ba5e,0xb365375e,0x3bc93b1a,0x35933b02,0x3b8037b7,
0x31db39fe,0x3bdd394d,0x3b5a3bbc,0x364eb414,0xbb46b75e,0x36aa3b1a,0xb11537b7,0x3be63b02,0xb900bbc9,0xba3fb365,0xbbf8b9dc,0x2d7e3972,0x38d8a248,0xba5ebc00,0xb534bab5,0xbb91b85d,
0x3807ad7e,0xbae9bbf8,0xb9febbf4,0xb94daf0e,0x3bdd3b46,0x31dbb6aa,0x35f1b365,0xbb6ebbc9,0x31153996,0x3be639ba,0x3bff3ab5,0x28b6b85d,0xbb02b705,0x37b73b30,0x34d53a5e,0x3ba038d8,
0xbb91b900,0x35343a3f,0x38073b1a,0x3ae9375e,0xb996bbc9,0xb9bab365,0xb887a8b6,0x3a993bff,0x3593b2a1,0xbb80bbd4,0xbbe6bb5a,0xb115364e,0x3bf83a5e,0xad7eb8d8,0xb475b9fe,0xbbafb94d,
0x3b6e3bed,0x35f1b04e,0xb2a1b94d,0xbbd4b9fe,0x31153900,0x3be63a3f,0x39dc34d5,0xb972bba0,0xba1fb593,0x39273b80,0x3baf3bc9,0x3475b365,0xbb91bbdd,0xb53431db,0x34143996,0x3bbc39ba,
0xb75eba7c,0xbb1ab8b0,0xaf0e3593,0x3bf43b80,0x3705a248,0xbb30bc00,0xbae9b85d,0x38073ab5,0x3bdd3a5e,0xb1dbb8d8,0xbb5abbfc,0xb64e2bd9,0x39dc3baf,0x39723475,0xb365b927,0xbbc9ba1f,
0xb36531db,0x3bc93bdd,0x36aa2248,0xbb46bc00,0xbb02b8d8,0x37b73a5e,0x3ba039fe,0xb4d5b94d,0xbb91bbf8,0xb5342d7e,0x3ae93bf4,0x38072f0e,0xb64eb9dc,0xbb5ab972,0x32a138b0,0x3bd43a7c,
0x3a7c385d,0xb8b0bab5,0xb972b5f1,0x39dc3b6e,0x3bf43bbc,0x2f0eb414,0xbbf8bb30,0x2d7e3705,0x394d3b1a,0x39fe375e,0xba5ebbaf,0xb8d8b475,0xa2483593,0x3c003b80,0xb1dbb832,0xbbddbad0,
0xbbf8bbc9,0xad7e3365,0x3b023972,0xb7b7b9dc,0xb9febb5a,0xb94db64e,0x3bed3bdd,0x304eb1db,0xb2a1b807,0xbbd4bae9,0x39ba3b30,0x39963705,0x36aa2f0e,0xbb46bbf4,0x3115375e,0x3be63b1a,
0x39963ae9,0x39ba3807,0xbbddbb30,0x31db3705,0x336537b7,0x3bc93b02,0xbb80bbf8,0xb593ad7e,0xb4d5a8b6,0x3ba03bff,0xb900ba7c,0xba3fb8b0,0xb9feb85d,0x394d3ab5,0xb04eb64e,0xbbedbb5a,
0xabd9b475,0xbbfcbbaf,0x3bed3bf8,0x304ead7e,0x35f13115,0xbb6ebbe6,0x3ab53b80,0x385d3593,0x39dc3887,0xb972ba99,0x38323996,0x3ad039ba,0x3ba03ae9,0xb4d5b807,0x2f0e3534,0x3bf43b91,
0xb8d8b75e,0x3a5e3b1a,0xbb30bbaf,0xb705b475,0xbab5b9dc,0x385d3972,0xb996ba7c,0xb9bab8b0,0xbbc9bb5a,0x3365364e,0xb6aab887,0xbb46ba99,0xbbf4bbfc,0xaf0e2bd9,0xad7eb414,0xbbf8bbbc,
0x3bd43b91,0xb2a1b534,0x39ba3a5e,0x399638d8,0x3bff3bf8,0x28b6ad7e,0x38323900,0x3ad03a3f,0x3baf3be6,0x34753115,0x34d536aa,0x3ba03b46,0x3ae93b5a,0x3807364e,0x2bd931db,0x3bfc3bdd,
0xbb02bb46,0xb7b7b6aa,0xb75eb832,0xbb1abad0,0xba5ebab5,0xb8d8b85d,0xb534b64e,0xbb91bb5a,0xb996b9fe,0xb9bab94d,0xb1dbb414,0xbbddbbbc,0xb8b0b927,0xba7cba1f,0xa8b6af0e,0xbbffbbf4,
0x359335f1,0x3b803b6e,0x311531db,0x3be63bdd,0x34d53534,0x3ba03b91,0x2f0e304e,0x3bf43bed,0x34143475,0x3bbc3baf,0x2bd92d7e,0x3bfc3bf8,0x32a13365,0x3bd43bc9,0x224828b6,0x3c003bff,
0x80000,0x680060,0xc800c0,0x1280120,0xc0004,0x6c0064,0xcc00c4,0x12c0124,0x180010,0x780070,0xd800d0,0x1380130,0x1c0014,0x7c0074,0xdc00d4,0x13c0134,
0x1900188,0x1f001e8,0x2500248,0x2b002a8,0x194018c,0x1f401ec,0x254024c,0x2b402ac,0x1a00198,0x20001f8,0x2600258,0x2c002b8,0x1a4019c,0x20401fc,0x264025c,0x2c402bc,
0x3180310,0x3780370,0x3d803d0,0x4380430,0x31c0314,0x37c0374,0x3dc03d4,0x43c0434,0x3280320,0x3880380,0x3e803e0,0x4480440,0x32c0324,0x38c0384,0x3ec03e4,0x44c0444,
0x4a00498,0x50004f8,0x5600558,0x5c005b8,0x4a4049c,0x50404fc,0x564055c,0x5c405bc,0x4b004a8,0x5100508,0x5700568,0x5d005c8,0x4b404ac,0x514050c,0x574056c,0x5d405cc,
0x6280620,0x6880680,0x6e806e0,0x7480740,0x62c0624,0x68c0684,0x6ec06e4,0x74c0744,0x6380630,0x6980690,0x6f806f0,0x7580750,0x63c0634,0x69c0694,0x6fc06f4,0x75c0754,
0x7b007a8,0x8100808,0x8700868,0x8d008c8,0x7b407ac,0x814080c,0x874086c,0x8d408cc,0x7c007b8,0x8200818,0x8800878,0x8e008d8,0x7c407bc,0x824081c,0x884087c,0x8e408dc,
0x9380930,0x9980990,0x9f809f0,0xa580a50,0x93c0934,0x99c0994,0x9fc09f4,0xa5c0a54,0x9480940,0x9a809a0,0xa080a00,0xa680a60,0x94c0944,0x9ac09a4,0xa0c0a04,0xa6c0a64,
0xac00ab8,0xb200b18,0xb800b78,0xbe00bd8,0xac40abc,0xb240b1c,0xb840b7c,0xbe40bdc,0xad00ac8,0xb300b28,0xb900b88,0xbf00be8,0xad40acc,0xb340b2c,0xb940b8c,0xbf40bec,
0x280020,0x880080,0xe800e0,0x1480140,0x2c0024,0x8c0084,0xec00e4,0x14c0144,0x240020,0x840080,0xe400e0,0x1440140,0x800024,0xe00084,0x14000e4,0x1a80144,
0x1b001a8,0x2100208,0x2700268,0x2d002c8,0x1b401ac,0x214020c,0x274026c,0x2d402cc,0x1ac01a8,0x20c0208,0x26c0268,0x2cc02c8,0x20801ac,0x268020c,0x2c8026c,0x33002cc,
0x3380330,0x3980390,0x3f803f0,0x4580450,0x33c0334,0x39c0394,0x3fc03f4,0x45c0454,0x3340330,0x3940390,0x3f403f0,0x4540450,0x3900334,0x3f00394,0x45003f4,0x4b80454,
0x4c004b8,0x5200518,0x5800578,0x5e005d8,0x4c404bc,0x524051c,0x584057c,0x5e405dc,0x4bc04b8,0x51c0518,0x57c0578,0x5dc05d8,0x51804bc,0x578051c,0x5d8057c,0x64005dc,
0x6480640,0x6a806a0,0x7080700,0x7680760,0x64c0644,0x6ac06a4,0x70c0704,0x76c0764,0x6440640,0x6a406a0,0x7040700,0x7640760,0x6a00644,0x70006a4,0x7600704,0x7c80764,
0x7d007c8,0x8300828,0x8900888,0x8f008e8,0x7d407cc,0x834082c,0x894088c,0x8f408ec,0x7cc07c8,0x82c0828,0x88c0888,0x8ec08e8,0x82807cc,0x888082c,0x8e8088c,0x95008ec,
0x9580950,0x9b809b0,0xa180a10,0xa780a70,0x95c0954,0x9bc09b4,0xa1c0a14,0xa7c0a74,0x9540950,0x9b409b0,0xa140a10,0xa740a70,0x9b00954,0xa1009b4,0xa700a14,0xad80a74,
0xae00ad8,0xb400b38,0xba00b98,0xc000bf8,0xae40adc,0xb440b3c,0xba40b9c,0xc040bfc,0xadc0ad8,0xb3c0b38,0xb9c0b98,0xbfc0bf8,0xb380adc,0xb980b3c,0xbf80b9c,0x300bfc,
0x300030,0x900090,0xf000f0,0x1500150,0x900034,0xf00094,0x15000f4,0x1b80154,0x340030,0x940090,0xf400f0,0x1540150,0x900034,0xf00094,0x15000f4,0x1b80154,
0x1b801b8,0x2180218,0x2780278,0x2d802d8,0x21801bc,0x278021c,0x2d8027c,0x34002dc,0x1bc01b8,0x21c0218,0x27c0278,0x2dc02d8,0x21801bc,0x278021c,0x2d8027c,0x34002dc,
0x3400340,0x3a003a0,0x4000400,0x4600460,0x3a00344,0x40003a4,0x4600404,0x4c80464,0x3440340,0x3a403a0,0x4040400,0x4640460,0x3a00344,0x40003a4,0x4600404,0x4c80464,
0x4c804c8,0x5280528,0x5880588,0x5e805e8,0x52804cc,0x588052c,0x5e8058c,0x65005ec,0x4cc04c8,0x52c0528,0x58c0588,0x5ec05e8,0x52804cc,0x588052c,0x5e8058c,0x65005ec,
0x6500650,0x6b006b0,0x7100710,0x7700770,0x6b00654,0x71006b4,0x7700714,0x7d80774,0x6540650,0x6b406b0,0x7140710,0x7740770,0x6b00654,0x71006b4,0x7700714,0x7d80774,
0x7d807d8,0x8380838,0x8980898,0x8f808f8,0x83807dc,0x898083c,0x8f8089c,0x96008fc,0x7dc07d8,0x83c0838,0x89c0898,0x8fc08f8,0x83807dc,0x898083c,0x8f8089c,0x96008fc,
0x9600960,0x9c009c0,0xa200a20,0xa800a80,0x9c00964,0xa2009c4,0xa800a24,0xae80a84,0x9640960,0x9c409c0,0xa240a20,0xa840a80,0x9c00964,0xa2009c4,0xa800a24,0xae80a84,
0xae80ae8,0xb480b48,0xba80ba8,0xc080c08,0xb480aec,0xba80b4c,0xc080bac,0x380c0c,0xaec0ae8,0xb4c0b48,0xbac0ba8,0xc0c0c08,0xb480aec,0xba80b4c,0xc080bac,0x380c0c,
0x380038,0x980098,0xf800f8,0x1580158,0x98003c,0xf8009c,0x15800fc,0x1c0015c,0x3c0038,0x9c0098,0xfc00f8,0x15c0158,0x98003c,0xf8009c,0x15800fc,0x1c0015c,
0x1c001c0,0x2200220,0x2800280,0x2e002e0,0x22001c4,0x2800224,0x2e00284,0x34802e4,0x1c401c0,0x2240220,0x2840280,0x2e402e0,0x22001c4,0x2800224,0x2e00284,0x34802e4,
0x3480348,0x3a803a8,0x4080408,0x4680468,0x3a8034c,0x40803ac,0x468040c,0x4d0046c,0x34c0348,0x3ac03a8,0x40c0408,0x46c0468,0x3a8034c,0x40803ac,0x468040c,0x4d0046c,
0x4d004d0,0x5300530,0x5900590,0x5f005f0,0x53004d4,0x5900534,0x5f00594,0x65805f4,0x4d404d0,0x5340530,0x5940590,0x5f405f0,0x53004d4,0x5900534,0x5f00594,0x65805f4,
0x6580658,0x6b806b8,0x7180718,0x7780778,0x6b8065c,0x71806bc,0x778071c,0x7e0077c,0x65c0658,0x6bc06b8,0x71c0718,0x77c0778,0x6b8065c,0x71806bc,0x778071c,0x7e0077c,
0x7e007e0,0x8400840,0x8a008a0,0x9000900,0x84007e4,0x8a00844,0x90008a4,0x9680904,0x7e407e0,0x8440840,0x8a408a0,0x9040900,0x84007e4,0x8a00844,0x90008a4,0x9680904,
0x9680968,0x9c809c8,0xa280a28,0xa880a88,0x9c8096c,0xa2809cc,0xa880a2c,0xaf00a8c,0x96c0968,0x9cc09c8,0xa2c0a28,0xa8c0a88,0x9c8096c,0xa2809cc,0xa880a2c,0xaf00a8c,
0xaf00af0,0xb500b50,0xbb00bb0,0xc100c10,0xb500af4,0xbb00b54,0xc100bb4,0x400c14,0xaf40af0,0xb540b50,0xbb40bb0,0xc140c10,0xb500af4,0xbb00b54,0xc100bb4,0x400c14,
0xb040b04,0xb640b64,0xbc40bc4,0xc240c24,0xb640b04,0xbc40bc4,0xc240bc4,0x500050,0xb040b04,0xb640b64,0xbc40bc4,0xc240c24,0xb640b64,0xbc40bc4,0xc240c24,0x500050,
0x97c097c,0x9dc09dc,0xa3c0a3c,0xa9c0a9c,0x9dc097c,0xa3c0a3c,0xa9c0a3c,0xb040b04,0x97c097c,0x9dc09dc,0xa3c0a3c,0xa9c0a9c,0x9dc09dc,0xa3c0a3c,0xa9c0a9c,0xb040b04,
0x7f407f4,0x8540854,0x8b408b4,0x9140914,0x85407f4,0x8b408b4,0x91408b4,0x97c097c,0x7f407f4,0x8540854,0x8b408b4,0x9140914,0x8540854,0x8b408b4,0x9140914,0x97c097c,
0x66c066c,0x6cc06cc,0x72c072c,0x78c078c,0x6cc066c,0x72c072c,0x78c072c,0x7f407f4,0x66c066c,0x6cc06cc,0x72c072c,0x78c078c,0x6cc06cc,0x72c072c,0x78c078c,0x7f407f4,
0x4e404e4,0x5440544,0x5a405a4,0x6040604,0x54404e4,0x5a405a4,0x60405a4,0x66c066c,0x4e404e4,0x5440544,0x5a405a4,0x6040604,0x5440544,0x5a405a4,0x6040604,0x66c066c,
0x35c035c,0x3bc03bc,0x41c041c,0x47c047c,0x3bc035c,0x41c041c,0x47c041c,0x4e404e4,0x35c035c,0x3bc03bc,0x41c041c,0x47c047c,0x3bc03bc,0x41c041c,0x47c047c,0x4e404e4,
0x1d401d4,0x2340234,0x2940294,0x2f402f4,0x23401d4,0x2940294,0x2f40294,0x35c035c,0x1d401d4,0x2340234,0x2940294,0x2f402f4,0x2340234,0x2940294,0x2f402f4,0x35c035c,
0x4c004c,0xac00ac,0x10c010c,0x16c016c,0xac004c,0x10c010c,0x16c010c,0x1d401d4,0x4c004c,0xac00ac,0x10c010c,0x16c016c,0xac00ac,0x10c010c,0x16c016c,0x1d401d4,
0xb000b00,0xb600b60,0xbc00bc0,0xc200c20,0xb600b00,0xbc00bc0,0xc200bc0,0x4c004c,0xb000b00,0xb600b60,0xbc00bc0,0xc200c20,0xb600b60,0xbc00bc0,0xc200c20,0x4c004c,
0x9780978,0x9d809d8,0xa380a38,0xa980a98,0x9d80978,0xa380a38,0xa980a38,0xb000b00,0x9780978,0x9d809d8,0xa380a38,0xa980a98,0x9d809d8,0xa380a38,0xa980a98,0xb000b00,
0x7f007f0,0x8500850,0x8b008b0,0x9100910,0x85007f0,0x8b008b0,0x91008b0,0x9780978,0x7f007f0,0x8500850,0x8b008b0,0x9100910,0x8500850,0x8b008b0,0x9100910,0x9780978,
0x6680668,0x6c806c8,0x7280728,0x7880788,0x6c80668,0x7280728,0x7880728,0x7f007f0,0x6680668,0x6c806c8,0x7280728,0x7880788,0x6c806c8,0x7280728,0x7880788,0x7f007f0,
0x4e004e0,0x5400540,0x5a005a0,0x6000600,0x54004e0,0x5a005a0,0x60005a0,0x6680668,0x4e004e0,0x5400540,0x5a005a0,0x6000600,0x5400540,0x5a005a0,0x6000600,0x6680668,
0x3580358,0x3b803b8,0x4180418,0x4780478,0x3b80358,0x4180418,0x4780418,0x4e004e0,0x3580358,0x3b803b8,0x4180418,0x4780478,0x3b803b8,0x4180418,0x4780478,0x4e004e0,
0x1d001d0,0x2300230,0x2900290,0x2f002f0,0x23001d0,0x2900290,0x2f00290,0x3580358,0x1d001d0,0x2300230,0x2900290,0x2f002f0,0x2300230,0x2900290,0x2f002f0,0x3580358,
0x480048,0xa800a8,0x1080108,0x1680168,0xa80048,0x1080108,0x1680108,0x1d001d0,0x480048,0xa800a8,0x1080108,0x1680168,0xa800a8,0x1080108,0x1680168,0x1d001d0,
0xafc0afc,0xb5c0b5c,0xbbc0bbc,0xc1c0c1c,0xb5c0afc,0xbbc0bbc,0xc1c0bbc,0x480048,0xafc0afc,0xb5c0b5c,0xbbc0bbc,0xc1c0c1c,0xb5c0b5c,0xbbc0bbc,0xc1c0c1c,0x480048,
0x9740974,0x9d409d4,0xa340a34,0xa940a94,0x9d40974,0xa340a34,0xa940a34,0xafc0afc,0x9740974,0x9d409d4,0xa340a34,0xa940a94,0x9d409d4,0xa340a34,0xa940a94,0xafc0afc,
0x7ec07ec,0x84c084c,0x8ac08ac,0x90c090c,0x84c07ec,0x8ac08ac,0x90c08ac,0x9740974,0x7ec07ec,0x84c084c,0x8ac08ac,0x90c090c,0x84c084c,0x8ac08ac,0x90c090c,0x9740974,
0x6640664,0x6c406c4,0x7240724,0x7840784,0x6c40664,0x7240724,0x7840724,0x7ec07ec,0x6640664,0x6c406c4,0x7240724,0x7840784,0x6c406c4,0x7240724,0x7840784,0x7ec07ec,
0x4dc04dc,0x53c053c,0x59c059c,0x5fc05fc,0x53c04dc,0x59c059c,0x5fc059c,0x6640664,0x4dc04dc,0x53c053c,0x59c059c,0x5fc05fc,0x53c053c,0x59c059c,0x5fc05fc,0x6640664,
0x3540354,0x3b403b4,0x4140414,0x4740474,0x3b40354,0x4140414,0x4740414,0x4dc04dc,0x3540354,0x3b403b4,0x4140414,0x4740474,0x3b403b4,0x4140414,0x4740474,0x4dc04dc,
0x1cc01cc,0x22c022c,0x28c028c,0x2ec02ec,0x22c01cc,0x28c028c,0x2ec028c,0x3540354,0x1cc01cc,0x22c022c,0x28c028c,0x2ec02ec,0x22c022c,0x28c028c,0x2ec02ec,0x3540354,
0x440044,0xa400a4,0x1040104,0x1640164,0xa40044,0x1040104,0x1640104,0x1cc01cc,0x440044,0xa400a4,0x1040104,0x1640164,0xa400a4,0x1040104,0x1640164,0x1cc01cc,
0xaf80af8,0xb580b58,0xbb80bb8,0xc180c18,0xb580af8,0xbb80bb8,0xc180bb8,0x440044,0xaf80af8,0xb580b58,0xbb80bb8,0xc180c18,0xb580b58,0xbb80bb8,0xc180c18,0x440044,
0x9700970,0x9d009d0,0xa300a30,0xa900a90,0x9d00970,0xa300a30,0xa900a30,0xaf80af8,0x9700970,0x9d009d0,0xa300a30,0xa900a90,0x9d009d0,0xa300a30,0xa900a90,0xaf80af8,
0x7e807e8,0x8480848,0x8a808a8,0x9080908,0x84807e8,0x8a808a8,0x90808a8,0x9700970,0x7e807e8,0x8480848,0x8a808a8,0x9080908,0x8480848,0x8a808a8,0x9080908,0x9700970,
0x6600660,0x6c006c0,0x7200720,0x7800780,0x6c00660,0x7200720,0x7800720,0x7e807e8,0x6600660,0x6c006c0,0x7200720,0x7800780,0x6c006c0,0x7200720,0x7800780,0x7e807e8,
0x4d804d8,0x5380538,0x5980598,0x5f805f8,0x53804d8,0x5980598,0x5f80598,0x6600660,0x4d804d8,0x5380538,0x5980598,0x5f805f8,0x5380538,0x5980598,0x5f805f8,0x6600660,
0x3500350,0x3b003b0,0x4100410,0x4700470,0x3b00350,0x4100410,0x4700410,0x4d804d8,0x3500350,0x3b003b0,0x4100410,0x4700470,0x3b003b0,0x4100410,0x4700470,0x4d804d8,
0x1c801c8,0x2280228,0x2880288,0x2e802e8,0x22801c8,0x2880288,0x2e80288,0x3500350,0x1c801c8,0x2280228,0x2880288,0x2e802e8,0x2280228,0x2880288,0x2e802e8,0x3500350,
0x400040,0xa000a0,0x1000100,0x1600160,0xa00040,0x1000100,0x1600100,0x1c801c8,0x400040,0xa000a0,0x1000100,0x1600160,0xa000a0,0x1000100,0x1600160,0x1c801c8,
0x30003000,0x30003000,0x30003000,0x30003000,0x30003000,0x30003000,0x30003000,0x30003000,0x0,0x0,0x0,0x0,0x0,0x0,0x0,0x0,
0x30003000,0x30003000,0x30003000,0x30003000,0x30003000,0x30003000,0x30003000,0x30003000,0x0,0x0,0x0,0x0,0x0,0x0,0x0,0x0,
0x2a1f2da8,0xaf64ada8,0xaa1fada8,0x2f642da8,0x2f643000,0xaa1f0000,0xaf64b000,0x2a1f8000,0x2f642da8,0x2a1f2da8,0xaf64ada8,0xaa1fada8,0x2a1f0000,0x2f643000,0xaa1f0000,0xaf64b000,
0x263e2c72,0xafd9aea7,0xa63eac72,0x2fd92ea7,0x2ea72fd9,0xac72a63e,0xaea7afd9,0x2c72263e,0x2fd92ea7,0x263e2c72,0xafd9aea7,0xa63eac72,0x2c72263e,0x2ea72fd9,0xac72a63e,0xaea7afd9,
0x2da80000,0xada80000,0x2da88000,0xada80000,0x2da83000,0xada8b000,0x2da83000,0xada8b000,0x2da83000,0xada8b000,0x2da83000,0xada8b000,0xada80000,0x2da88000,0xada80000,0x2da88000,
0x2f642a1f,0xaf64aa1f,0x2f642a1f,0xaf64aa1f,0x2a1f2f64,0xaa1faf64,0x2a1f2f64,0xaa1faf64,0x2a1f2f64,0xaa1faf64,0x2a1f2f64,0xaa1faf64,0xaf64aa1f,0x2f642a1f,0xaf64aa1f,0x2f642a1f,
0xaa1f2da8,0x2f642da8,0x2a1fada8,0xaf64ada8,0x2f640000,0xaa1fb000,0xaf640000,0x2a1f3000,0xaf64ada8,0xaa1f2da8,0x2f642da8,0x2a1fada8,0x2a1f3000,0x2f648000,0xaa1fb000,0xaf640000,
0xaea7263e,0x2c722fd9,0x2ea7a63e,0xac72afd9,0x2fd92c72,0x263eaea7,0xafd9ac72,0xa63e2ea7,0xac72afd9,0xaea7263e,0x2c722fd9,0x2ea7a63e,0xa63e2ea7,0x2fd92c72,0x263eaea7,0xafd9ac72,
0xada82da8,0xada82da8,0xada82da8,0xada82da8,0x2da8ada8,0x2da8ada8,0x2da8ada8,0x2da8ada8,0x2da82da8,0x2da82da8,0x2da82da8,0x2da82da8,0xada8ada8,0xada8ada8,0xada8ada8,0xada8ada8,
0x3000,0x3000,0x3000,0x80003000,0x8000b000,0x8000b000,0x8000b000,0x8000b000,0x30000000,0x30008000,0x30008000,0x30008000,0xb0000000,0xb0000000,0xb0000000,0xb0000000,
0x2ea7263e,0xac722fd9,0xaea7a63e,0x2c72afd9,0xafd92c72,0xa63eaea7,0x2fd9ac72,0x263e2ea7,0x2c72afd9,0x2ea7263e,0xac722fd9,0xaea7a63e,0x263e2ea7,0xafd92c72,0xa63eaea7,0x2fd9ac72,
0x2f64ada8,0x2a1f2da8,0xaf642da8,0xaa1fada8,0xaa1f3000,0xaf640000,0x2a1fb000,0x2f648000,0xaa1fada8,0x2f64ada8,0x2a1f2da8,0xaf642da8,0x2f640000,0xaa1f3000,0xaf640000,0x2a1fb000,
0xaa1f2f64,0x2a1faf64,0xaa1f2f64,0x2a1faf64,0x2f64aa1f,0xaf642a1f,0x2f64aa1f,0xaf642a1f,0xaf642a1f,0x2f64aa1f,0xaf642a1f,0x2f64aa1f,0xaa1f2f64,0x2a1faf64,0xaa1f2f64,0x2a1faf64,
0x2da80000,0xada80000,0x2da88000,0xada80000,0x2da8b000,0xada83000,0x2da8b000,0xada83000,0xada83000,0x2da8b000,0xada83000,0x2da8b000,0x2da88000,0xada80000,0x2da88000,0xada88000,
0xa63e2c72,0x2fd9aea7,0x263eac72,0xafd92ea7,0xaea72fd9,0x2c72a63e,0x2ea7afd9,0xac72263e,0xafd92ea7,0xa63e2c72,0x2fd9aea7,0x263eac72,0xac72263e,0xaea72fd9,0x2c72a63e,0x2ea7afd9,
0x2f64ada8,0x2a1fada8,0xaf642da8,0xaa1f2da8,0x2a1f0000,0x2f64b000,0xaa1f0000,0xaf643000,0xaa1f2da8,0x2f64ada8,0x2a1fada8,0xaf642da8,0xaf643000,0x2a1f8000,0x2f64b000,0xaa1f8000,
0xb0003000,0xb0003000,0xb0003000,0xb0003000,0xb0003000,0xb0003000,0xb0003000,0xb0003000,0x0,0x8000,0x8000,0x80008000,0x8000,0x8000,0x8000,0x8000,
0x80000000,0x80000000,0x80008000,0x80008000,0x80000000,0x80008000,0x80008000,0x80008000,0xb0003000,0xb0003000,0xb0003000,0xb0003000,0xb0003000,0xb0003000,0xb0003000,0xb0003000,
0xaa1f2da8,0x2f64ada8,0x2a1fada8,0xaf642da8,0xaf643000,0x2a1f0000,0x2f64b000,0xaa1f8000,0xaf642da8,0xaa1f2da8,0x2f64ada8,0x2a1fada8,0xaa1f0000,0xaf643000,0x2a1f0000,0x2f64b000,
0x2fd9aea7,0x263eac72,0xafd92ea7,0xa63e2c72,0x2c72a63e,0x2ea7afd9,0xac72263e,0xaea72fd9,0xa63e2c72,0x2fd9aea7,0x263eac72,0xafd92ea7,0xaea72fd9,0x2c72a63e,0x2ea7afd9,0xac72263e,
0xada80000,0x2da80000,0xada88000,0x2da80000,0xada83000,0x2da8b000,0xada83000,0x2da8b000,0xada83000,0x2da8b000,0xada83000,0x2da8b000,0x2da80000,0xada88000,0x2da88000,0xada88000,
0xaa1f2f64,0x2a1faf64,0xaa1f2f64,0x2a1faf64,0x2f64aa1f,0xaf642a1f,0x2f64aa1f,0xaf642a1f,0x2f64aa1f,0xaf642a1f,0x2f64aa1f,0xaf642a1f,0x2a1faf64,0xaa1f2f64,0x2a1faf64,0xaa1f2f64,
0x2a1f2da8,0xaf642da8,0xaa1fada8,0x2f64ada8,0xaf640000,0x2a1fb000,0x2f640000,0xaa1f3000,0x2f64ada8,0x2a1f2da8,0xaf642da8,0xaa1fada8,0xaa1f3000,0xaf648000,0x2a1fb000,0x2f640000,
0x2c72afd9,0x2ea7263e,0xac722fd9,0xaea7a63e,0x263e2ea7,0xafd92c72,0xa63eaea7,0x2fd9ac72,0xaea7a63e,0x2c72afd9,0x2ea7263e,0xac722fd9,0x2fd9ac72,0x263e2ea7,0xafd92c72,0xa63eaea7,
0x2da8ada8,0x2da8ada8,0x2da8ada8,0x2da8ada8,0xada82da8,0xada82da8,0xada82da8,0xada82da8,0x2da82da8,0x2da82da8,0x2da82da8,0x2da82da8,0xada8ada8,0xada8ada8,0xada8ada8,0xada8ada8,
0x80003000,0x80003000,0x80003000,0x3000,0xb000,0x8000b000,0xb000,0xb000,0xb0000000,0xb0008000,0xb0008000,0xb0008000,0x30000000,0x30000000,0x30000000,0x30008000,
0x2c722fd9,0x2ea7a63e,0xac72afd9,0xaea7263e,0x263eaea7,0xafd9ac72,0xa63e2ea7,0x2fd92c72,0xaea7263e,0x2c722fd9,0x2ea7a63e,0xac72afd9,0x2fd92c72,0x263eaea7,0xafd9ac72,0xa63e2ea7,
0xaf64ada8,0xaa1f2da8,0x2f642da8,0x2a1fada8,0x2a1f3000,0x2f648000,0xaa1fb000,0xaf648000,0x2a1fada8,0xaf64ada8,0xaa1f2da8,0x2f642da8,0xaf640000,0x2a1f3000,0x2f648000,0xaa1fb000,
0x2f642a1f,0xaf64aa1f,0x2f642a1f,0xaf64aa1f,0x2a1f2f64,0xaa1faf64,0x2a1f2f64,0xaa1faf64,0xaa1faf64,0x2a1f2f64,0xaa1faf64,0x2a1f2f64,0x2f642a1f,0xaf64aa1f,0x2f642a1f,0xaf64aa1f,
0xada80000,0x2da80000,0xada88000,0x2da88000,0xada8b000,0x2da83000,0xada8b000,0x2da83000,0x2da83000,0xada8b000,0x2da83000,0xada8b000,0xada88000,0x2da88000,0xada88000,0x2da80000,
0x2fd92ea7,0x263e2c72,0xafd9aea7,0xa63eac72,0x2c72263e,0x2ea72fd9,0xac72a63e,0xaea7afd9,0xa63eac72,0x2fd92ea7,0x263e2c72,0xafd9aea7,0xaea7afd9,0x2c72263e,0x2ea72fd9,0xac72a63e,
0xaf64ada8,0xaa1fada8,0x2f642da8,0x2a1f2da8,0xaa1f0000,0xaf64b000,0x2a1f0000,0x2f643000,0x2a1f2da8,0xaf64ada8,0xaa1fada8,0x2f642da8,0x2f643000,0xaa1f8000,0xaf64b000,0x2a1f0000,
0x80008000,0x80008000,0x80008000,0x80008000,0x80008000,0x80008000,0x80008000,0x80008000,0x30003000,0x30003000,0x30003000,0x30003000,0x30003000,0x30003000,0x30003000,0x30003000,
0x80008000,0x80008000,0x80008000,0x80008000,0x80008000,0x80008000,0x80008000,0x80008000,0x30003000,0x30003000,0x30003000,0x30003000,0x30003000,0x30003000,0x30003000,0x30003000,
0xaf64ada8,0xaa1fada8,0x2f642da8,0x2a1f2da8,0xaa1f8000,0xaf64b000,0x2a1f8000,0x2f643000,0x2a1f2da8,0xaf64ada8,0xaa1fada8,0x2f642da8,0x2f643000,0xaa1f0000,0xaf64b000,0x2a1f8000,
0xafd9aea7,0xa63eac72,0x2fd92ea7,0x263e2c72,0xac72a63e,0xaea7afd9,0x2c72263e,0x2ea72fd9,0x263e2c72,0xafd9aea7,0xa63eac72,0x2fd92ea7,0x2ea72fd9,0xac72a63e,0xaea7afd9,0x2c72263e,
0x2da83000,0xada8b000,0x2da83000,0xada8b000,0xada80000,0x2da88000,0xada80000,0x2da88000,0xada88000,0x2da88000,0xada80000,0x2da88000,0xada8b000,0x2da83000,0xada8b000,0x2da83000,
0x2a1f2f64,0xaa1faf64,0x2a1f2f64,0xaa1faf64,0xaf64aa1f,0x2f642a1f,0xaf64aa1f,0x2f642a1f,0xaf64aa1f,0x2f642a1f,0xaf64aa1f,0x2f642a1f,0xaa1faf64,0x2a1f2f64,0xaa1faf64,0x2a1f2f64,
0xaf64ada8,0xaa1f2da8,0x2f642da8,0x2a1fada8,0x2a1f3000,0x2f648000,0xaa1fb000,0xaf640000,0x2a1fada8,0xaf64ada8,0xaa1f2da8,0x2f642da8,0xaf648000,0x2a1f3000,0x2f648000,0xaa1fb000,
0xac72afd9,0xaea7263e,0x2c722fd9,0x2ea7a63e,0xa63e2ea7,0x2fd92c72,0x263eaea7,0xafd9ac72,0x2ea7a63e,0xac72afd9,0xaea7263e,0x2c722fd9,0xafd9ac72,0xa63e2ea7,0x2fd92c72,0x263eaea7,
0xada8ada8,0xada8ada8,0xada8ada8,0xada8ada8,0x2da82da8,0x2da82da8,0x2da82da8,0x2da82da8,0xada82da8,0xada82da8,0xada82da8,0xada82da8,0x2da8ada8,0x2da8ada8,0x2da8ada8,0x2da8ada8,
0xb0008000,0xb0000000,0xb0000000,0xb0000000,0x30008000,0x30008000,0x30008000,0x30008000,0x3000,0x3000,0x3000,0x80003000,0x8000b000,0x8000b000,0x8000b000,0x8000b000,
0xac722fd9,0xaea7a63e,0x2c72afd9,0x2ea7263e,0xa63eaea7,0x2fd9ac72,0x263e2ea7,0xafd92c72,0x2ea7263e,0xac722fd9,0xaea7a63e,0x2c72afd9,0xafd92c72,0xa63eaea7,0x2fd9ac72,0x263e2ea7,
0x2a1f2da8,0xaf642da8,0xaa1fada8,0x2f64ada8,0xaf648000,0x2a1fb000,0x2f648000,0xaa1f3000,0x2f64ada8,0x2a1f2da8,0xaf642da8,0xaa1fada8,0xaa1f3000,0xaf640000,0x2a1fb000,0x2f648000,
0xaf642a1f,0x2f64aa1f,0xaf642a1f,0x2f64aa1f,0xaa1f2f64,0x2a1faf64,0xaa1f2f64,0x2a1faf64,0x2a1faf64,0xaa1f2f64,0x2a1faf64,0xaa1f2f64,0xaf642a1f,0x2f64aa1f,0xaf642a1f,0x2f64aa1f,
0xada83000,0x2da8b000,0xada83000,0x2da8b000,0x2da88000,0xada80000,0x2da88000,0xada88000,0xada88000,0x2da88000,0xada80000,0x2da88000,0xada83000,0x2da8b000,0xada83000,0x2da8b000,
0xafd92ea7,0xa63e2c72,0x2fd9aea7,0x263eac72,0xac72263e,0xaea72fd9,0x2c72a63e,0x2ea7afd9,0x263eac72,0xafd92ea7,0xa63e2c72,0x2fd9aea7,0x2ea7afd9,0xac72263e,0xaea72fd9,0x2c72a63e,
0xaa1f2da8,0x2f64ada8,0x2a1fada8,0xaf642da8,0xaf643000,0x2a1f8000,0x2f64b000,0xaa1f8000,0xaf642da8,0xaa1f2da8,0x2f64ada8,0x2a1fada8,0xaa1f8000,0xaf643000,0x2a1f8000,0x2f64b000,
0x80008000,0x80000000,0x80000000,0x0,0x80000000,0x80000000,0x80000000,0x80000000,0xb0003000,0xb0003000,0xb0003000,0xb0003000,0xb0003000,0xb0003000,0xb0003000,0xb0003000,
0x3000b000,0x3000b000,0x3000b000,0x3000b000,0x3000b000,0x3000b000,0x3000b000,0x3000b000,0x80000000,0x80000000,0x80008000,0x80008000,0x80000000,0x80008000,0x80008000,0x80008000,
0x2f64ada8,0x2a1fada8,0xaf642da8,0xaa1f2da8,0x2a1f8000,0x2f64b000,0xaa1f8000,0xaf643000,0xaa1f2da8,0x2f64ada8,0x2a1fada8,0xaf642da8,0xaf643000,0x2a1f0000,0x2f64b000,0xaa1f8000,
0x263eac72,0xafd92ea7,0xa63e2c72,0x2fd9aea7,0x2ea7afd9,0xac72263e,0xaea72fd9,0x2c72a63e,0x2fd9aea7,0x263eac72,0xafd92ea7,0xa63e2c72,0x2c72a63e,0x2ea7afd9,0xac72263e,0xaea72fd9,
0xada83000,0x2da8b000,0xada83000,0x2da8b000,0x2da80000,0xada88000,0x2da88000,0xada88000,0x2da88000,0xada88000,0x2da80000,0xada88000,0x2da8b000,0xada83000,0x2da8b000,0xada83000,
0x2f64aa1f,0xaf642a1f,0x2f64aa1f,0xaf642a1f,0x2a1faf64,0xaa1f2f64,0x2a1faf64,0xaa1f2f64,0x2a1faf64,0xaa1f2f64,0x2a1faf64,0xaa1f2f64,0xaf642a1f,0x2f64aa1f,0xaf642a1f,0x2f64aa1f,
0x2f64ada8,0x2a1f2da8,0xaf642da8,0xaa1fada8,0xaa1f3000,0xaf648000,0x2a1fb000,0x2f640000,0xaa1fada8,0x2f64ada8,0x2a1f2da8,0xaf642da8,0x2f648000,0xaa1f3000,0xaf648000,0x2a1fb000,
0xaea7a63e,0x2c72afd9,0x2ea7263e,0xac722fd9,0x2fd9ac72,0x263e2ea7,0xafd92c72,0xa63eaea7,0xac722fd9,0xaea7a63e,0x2c72afd9,0x2ea7263e,0xa63eaea7,0x2fd9ac72,0x263e2ea7,0xafd92c72,
0xada8ada8,0xada8ada8,0xada8ada8,0xada8ada8,0x2da82da8,0x2da82da8,0x2da82da8,0x2da82da8,0x2da8ada8,0x2da8ada8,0x2da8ada8,0x2da8ada8,0xada82da8,0xada82da8,0xada82da8,0xada82da8,
0x30008000,0x30000000,0x30000000,0x30000000,0xb0008000,0xb0008000,0xb0008000,0xb0000000,0x80003000,0x80003000,0x80003000,0x3000,0xb000,0x8000b000,0xb000,0xb000,
0x2ea7a63e,0xac72afd9,0xaea7263e,0x2c722fd9,0xafd9ac72,0xa63e2ea7,0x2fd92c72,0x263eaea7,0x2c722fd9,0x2ea7a63e,0xac72afd9,0xaea7263e,0x263eaea7,0xafd9ac72,0xa63e2ea7,0x2fd92c72,
0xaa1f2da8,0x2f642da8,0x2a1fada8,0xaf64ada8,0x2f648000,0xaa1fb000,0xaf640000,0x2a1f3000,0xaf64ada8,0xaa1f2da8,0x2f642da8,0x2a1fada8,0x2a1f3000,0x2f648000,0xaa1fb000,0xaf648000,
0xaa1faf64,0x2a1f2f64,0xaa1faf64,0x2a1f2f64,0x2f642a1f,0xaf64aa1f,0x2f642a1f,0xaf64aa1f,0xaf64aa1f,0x2f642a1f,0xaf64aa1f,0x2f642a1f,0xaa1faf64,0x2a1f2f64,0xaa1faf64,0x2a1f2f64,
0x2da83000,0xada8b000,0x2da83000,0xada8b000,0xada88000,0x2da88000,0xada88000,0x2da80000,0x2da88000,0xada88000,0x2da80000,0xada80000,0x2da83000,0xada8b000,0x2da83000,0xada8b000,
0xa63eac72,0x2fd92ea7,0x263e2c72,0xafd9aea7,0xaea7afd9,0x2c72263e,0x2ea72fd9,0xac72a63e,0xafd9aea7,0xa63eac72,0x2fd92ea7,0x263e2c72,0xac72a63e,0xaea7afd9,0x2c72263e,0x2ea72fd9,
0x2a1f2da8,0xaf64ada8,0xaa1fada8,0x2f642da8,0x2f643000,0xaa1f8000,0xaf64b000,0x2a1f0000,0x2f642da8,0x2a1f2da8,0xaf64ada8,0xaa1fada8,0x2a1f8000,0x2f643000,0xaa1f8000,0xaf64b000,
0x3c003c00,0x3c003c00,0x3c003c00,0x3c003c00,0x3c003c00,0x3c003c00,0x3c003c00,0x3c003c00,0x80008000,0x80008000,0x80008000,0x80008000,0x80008000,0x80008000,0x80008000,0x80008000,
0x3bd93c00,0x3aa73b64,0x387239a8,0x323e361f,0xb23e0000,0xb872b61f,0xbaa7b9a8,0xbbd9bb64,0xb23e8000,0xb872b61f,0xbaa7b9a8,0xbbd9bb64,0xbbd9bc00,0xbaa7bb64,0xb872b9a8,0xb23eb61f,
0xbb64bc00,0xb61fb9a8,0x361f8000,0x3b6439a8,0x3b643c00,0x361f39a8,0xb61f0000,0xbb64b9a8,0x361f8000,0x3b6439a8,0x3b643c00,0x361f39a8,0xb61f8000,0xbb64b9a8,0xbb64bc00,0xb61fb9a8,
0x38728000,0x3bd93b64,0x323e39a8,0xbaa7b61f,0x3aa73c00,0xb23e361f,0xbbd9b9a8,0xb872bb64,0x3aa73c00,0xb23e361f,0xbbd9b9a8,0xb872bb64,0xb8728000,0xbbd9bb64,0xb23eb9a8,0x3aa7361f,
0xbc008000,0x3c008000,0xbc000000,0x3c008000,0xbc000000,0x3c008000,0xbc000000,0x3c008000,0x3c00,0x8000bc00,0x3c00,0x8000bc00,0x3c00,0x8000bc00,0x80003c00,0x8000bc00,
0xbbd98000,0x3aa7361f,0xb872b9a8,0x323e3b64,0x323ebc00,0xb8723b64,0x3aa7b9a8,0xbbd9361f,0xb23e3c00,0x3872bb64,0xbaa739a8,0x3bd9b61f,0xbbd90000,0x3aa7361f,0xb872b9a8,0x323e3b64,
0x3b648000,0xb61fb9a8,0xb61f3c00,0x3b64b9a8,0xbb648000,0x361f39a8,0x361fbc00,0xbb6439a8,0x361fbc00,0xbb6439a8,0x3b648000,0xb61fb9a8,0xb61f3c00,0x3b64b9a8,0xbb640000,0x361f39a8,
0xb8723c00,0x3bd9b61f,0xb23eb9a8,0xbaa73b64,0xbaa78000,0xb23e3b64,0x3bd9b9a8,0xb872b61f,0x3aa78000,0x323ebb64,0xbbd939a8,0x3872361f,0xb8723c00,0x3bd9b61f,0xb23eb9a8,0xbaa73b64,
0xbbd93c00,0xbaa73b64,0xb87239a8,0xb23e361f,0x323e8000,0x3872b61f,0x3aa7b9a8,0x3bd9bb64,0x323e8000,0x3872b61f,0x3aa7b9a8,0x3bd9bb64,0x3bd9bc00,0x3aa7bb64,0x3872b9a8,0x323eb61f,
0xbc003c00,0xbc003c00,0xbc003c00,0xbc003c00,0xbc003c00,0xbc003c00,0xbc003c00,0xbc003c00,0x80008000,0x80000000,0x80000000,0x80000000,0x80000000,0x80000000,0x0,0x80000000,
0xb8728000,0xbbd93b64,0xb23e39a8,0x3aa7b61f,0xbaa73c00,0x323e361f,0x3bd9b9a8,0x3872bb64,0xbaa73c00,0x323e361f,0x3bd9b9a8,0x3872bb64,0x38728000,0x3bd9bb64,0x323eb9a8,0xbaa7361f,
0x3b64bc00,0x361fb9a8,0xb61f8000,0xbb6439a8,0xbb643c00,0xb61f39a8,0x361f0000,0x3b64b9a8,0xb61f8000,0xbb6439a8,0xbb643c00,0xb61f39a8,0x361f8000,0x3b64b9a8,0x3b64bc00,0x361fb9a8,
0x3bd98000,0xbaa7361f,0x3872b9a8,0xb23e3b64,0xb23ebc00,0x38723b64,0xbaa7b9a8,0x3bd9361f,0x323e3c00,0xb872bb64,0x3aa739a8,0xbbd9b61f,0x3bd98000,0xbaa7361f,0x3872b9a8,0xb23e3b64,
0x3c008000,0xbc008000,0x3c000000,0xbc008000,0x3c000000,0xbc008000,0x3c000000,0xbc000000,0x80003c00,0xbc00,0x80003c00,0x8000bc00,0x80003c00,0xbc00,0x80003c00,0xbc00,
0x38723c00,0xbbd9b61f,0x323eb9a8,0x3aa73b64,0x3aa78000,0x323e3b64,0xbbd9b9a8,0x3872b61f,0xbaa78000,0xb23ebb64,0x3bd939a8,0xb872361f,0x38723c00,0xbbd9b61f,0x323eb9a8,0x3aa73b64,
0xbb640000,0x361fb9a8,0x361f3c00,0xbb64b9a8,0x3b648000,0xb61f39a8,0xb61fbc00,0x3b6439a8,0xb61fbc00,0x3b6439a8,0xbb640000,0x361fb9a8,0x361f3c00,0xbb64b9a8,0x3b648000,0xb61f39a8,
0x39a83c00,0xb9a80000,0xb9a8bc00,0x39a88000,0x39a83c00,0xb9a80000,0xb9a8bc00,0x39a88000,0xb9a88000,0xb9a8bc00,0x39a88000,0x39a83c00,0xb9a80000,0xb9a8bc00,0x39a88000,0x39a83c00,
0x38723c00,0xbbd9b61f,0x323eb9a8,0x3aa73b64,0xbaa70000,0xb23ebb64,0x3bd939a8,0xb872361f,0xbaa78000,0xb23ebb64,0x3bd939a8,0xb872361f,0xb872bc00,0x3bd9361f,0xb23e39a8,0xbaa7bb64,
0xb61fbc00,0x3b6439a8,0xbb640000,0x361fb9a8,0x361f3c00,0xbb64b9a8,0x3b648000,0xb61f39a8,0x3b648000,0xb61f39a8,0xb61fbc00,0x3b6439a8,0xbb648000,0x361fb9a8,0x361f3c00,0xbb64b9a8,
0x3bd98000,0xbaa7361f,0x3872b9a8,0xb23e3b64,0x323e3c00,0xb872bb64,0x3aa739a8,0xbbd9b61f,0x323e3c00,0xb872bb64,0x3aa739a8,0xbbd9b61f,0xbbd98000,0x3aa7b61f,0xb87239a8,0x323ebb64,
0xb9a88000,0xb9a83c00,0x39a88000,0x39a8bc00,0xb9a80000,0xb9a83c00,0x39a88000,0x39a8bc00,0xb9a83c00,0x39a88000,0x39a8bc00,0xb9a80000,0xb9a83c00,0x39a88000,0x39a8bc00,0xb9a88000,
0xb8728000,0xbbd93b64,0xb23e39a8,0x3aa7b61f,0x3aa7bc00,0xb23eb61f,0xbbd939a8,0xb8723b64,0xbaa73c00,0x323e361f,0x3bd9b9a8,0x3872bb64,0xb8728000,0xbbd93b64,0xb23e39a8,0x3aa7b61f,
0x361f8000,0x3b64b9a8,0x3b64bc00,0x361fb9a8,0xb61f8000,0xbb6439a8,0xbb643c00,0xb61f39a8,0x3b64bc00,0x361fb9a8,0xb61f8000,0xbb6439a8,0xbb643c00,0xb61f39a8,0x361f8000,0x3b64b9a8,
0xbbd93c00,0xbaa73b64,0xb87239a8,0xb23e361f,0xb23e8000,0xb872361f,0xbaa739a8,0xbbd93b64,0x323e8000,0x3872b61f,0x3aa7b9a8,0x3bd9bb64,0xbbd93c00,0xbaa73b64,0xb87239a8,0xb23e361f,
0xb8723c00,0x3bd9b61f,0xb23eb9a8,0xbaa73b64,0x3aa78000,0x323ebb64,0xbbd939a8,0x3872361f,0x3aa78000,0x323ebb64,0xbbd939a8,0x3872361f,0x3872bc00,0xbbd9361f,0x323e39a8,0x3aa7bb64,
0xb9a83c00,0x39a80000,0x39a8bc00,0xb9a88000,0xb9a83c00,0x39a88000,0x39a8bc00,0xb9a88000,0x39a88000,0x39a8bc00,0xb9a88000,0xb9a83c00,0x39a80000,0x39a8bc00,0xb9a88000,0xb9a83c00,
0xbbd98000,0x3aa7361f,0xb872b9a8,0x323e3b64,0xb23e3c00,0x3872bb64,0xbaa739a8,0x3bd9b61f,0xb23e3c00,0x3872bb64,0xbaa739a8,0x3bd9b61f,0x3bd98000,0xbaa7b61f,0x387239a8,0xb23ebb64,
0x361fbc00,0xbb6439a8,0x3b640000,0xb61fb9a8,0xb61f3c00,0x3b64b9a8,0xbb648000,0x361f39a8,0xbb648000,0x361f39a8,0x361fbc00,0xbb6439a8,0x3b648000,0xb61fb9a8,0xb61f3c00,0x3b64b9a8,
0x38728000,0x3bd93b64,0x323e39a8,0xbaa7b61f,0xbaa7bc00,0x323eb61f,0x3bd939a8,0x38723b64,0x3aa73c00,0xb23e361f,0xbbd9b9a8,0xb872bb64,0x38728000,0x3bd93b64,0x323e39a8,0xbaa7b61f,
0x39a88000,0x39a83c00,0xb9a88000,0xb9a8bc00,0x39a80000,0x39a83c00,0xb9a80000,0xb9a8bc00,0x39a83c00,0xb9a88000,0xb9a8bc00,0x39a88000,0x39a83c00,0xb9a88000,0xb9a8bc00,0x39a80000,
0x3bd93c00,0x3aa73b64,0x387239a8,0x323e361f,0x323e8000,0x3872361f,0x3aa739a8,0x3bd93b64,0xb23e8000,0xb872b61f,0xbaa7b9a8,0xbbd9bb64,0x3bd93c00,0x3aa73b64,0x387239a8,0x323e361f,
0xb61f8000,0xbb64b9a8,0xbb64bc00,0xb61fb9a8,0x361f8000,0x3b6439a8,0x3b643c00,0x361f39a8,0xbb64bc00,0xb61fb9a8,0x361f0000,0x3b6439a8,0x3b643c00,0x361f39a8,0xb61f8000,0xbb64b9a8,
0x0,0x0,0x0,0x0,0x0,0x0,0x0,0x0,0x3c003c00,0x3c003c00,0x3c003c00,0x3c003c00,0x3c003c00,0x3c003c00,0x3c003c00,0x3c003c00,
0x323e0000,0x3872361f,0x3aa739a8,0x3bd93b64,0x3bd93c00,0x3aa73b64,0x387239a8,0x323e361f,0x3bd93c00,0x3aa73b64,0x387239a8,0x323e361f,0xb23e0000,0xb872b61f,0xbaa7b9a8,0xbbd9bb64,
0xb61f0000,0xbb64b9a8,0xbb64bc00,0xb61fb9a8,0x361f0000,0x3b6439a8,0x3b643c00,0x361f39a8,0xbb64bc00,0xb61fb9a8,0x361f8000,0x3b6439a8,0x3b643c00,0x361f39a8,0xb61f0000,0xbb64b9a8,
0xbaa7bc00,0x323eb61f,0x3bd939a8,0x38723b64,0x38720000,0x3bd93b64,0x323e39a8,0xbaa7b61f,0x38728000,0x3bd93b64,0x323e39a8,0xbaa7b61f,0x3aa73c00,0xb23e361f,0xbbd9b9a8,0xb872bb64,
0x3c00,0x8000bc00,0x3c00,0x8000bc00,0x3c00,0x8000bc00,0x80003c00,0x8000bc00,0x3c000000,0xbc000000,0x3c008000,0xbc000000,0x3c008000,0xbc000000,0x3c008000,0xbc000000,
0xb23e3c00,0x3872bb64,0xbaa739a8,0x3bd9b61f,0xbbd90000,0x3aa7361f,0xb872b9a8,0x323e3b64,0x3bd90000,0xbaa7b61f,0x387239a8,0xb23ebb64,0xb23e3c00,0x3872bb64,0xbaa739a8,0x3bd9b61f,
0x361fbc00,0xbb6439a8,0x3b648000,0xb61fb9a8,0xb61f3c00,0x3b64b9a8,0xbb640000,0x361f39a8,0xbb640000,0x361f39a8,0x361fbc00,0xbb6439a8,0x3b640000,0xb61fb9a8,0xb61f3c00,0x3b64b9a8,
0x3aa78000,0x323ebb64,0xbbd939a8,0x3872361f,0xb8723c00,0x3bd9b61f,0xb23eb9a8,0xbaa73b64,0x3872bc00,0xbbd9361f,0x323e39a8,0x3aa7bb64,0x3aa70000,0x323ebb64,0xbbd939a8,0x3872361f,
0xb23e0000,0xb872361f,0xbaa739a8,0xbbd93b64,0xbbd93c00,0xbaa73b64,0xb87239a8,0xb23e361f,0xbbd93c00,0xbaa73b64,0xb87239a8,0xb23e361f,0x323e8000,0x3872b61f,0x3aa7b9a8,0x3bd9bb64,
0x0,0x8000,0x8000,0x8000,0x8000,0x8000,0x80008000,0x8000,0xbc003c00,0xbc003c00,0xbc003c00,0xbc003c00,0xbc003c00,0xbc003c00,0xbc003c00,0xbc003c00,
0x3aa7bc00,0xb23eb61f,0xbbd939a8,0xb8723b64,0xb8720000,0xbbd93b64,0xb23e39a8,0x3aa7b61f,0xb8728000,0xbbd93b64,0xb23e39a8,0x3aa7b61f,0xbaa73c00,0x323e361f,0x3bd9b9a8,0x3872bb64,
0x361f0000,0x3b64b9a8,0x3b64bc00,0x361fb9a8,0xb61f0000,0xbb6439a8,0xbb643c00,0xb61f39a8,0x3b64bc00,0x361fb9a8,0xb61f8000,0xbb6439a8,0xbb643c00,0xb61f39a8,0x361f0000,0x3b64b9a8,
0x323e3c00,0xb872bb64,0x3aa739a8,0xbbd9b61f,0x3bd98000,0xbaa7361f,0x3872b9a8,0xb23e3b64,0xbbd90000,0x3aa7b61f,0xb87239a8,0x323ebb64,0x323e3c00,0xb872bb64,0x3aa739a8,0xbbd9b61f,
0x80003c00,0xbc00,0x80003c00,0x8000bc00,0x80003c00,0xbc00,0x80003c00,0xbc00,0xbc000000,0x3c000000,0xbc008000,0x3c000000,0xbc008000,0x3c000000,0xbc008000,0x3c008000,
0xbaa78000,0xb23ebb64,0x3bd939a8,0xb872361f,0x38723c00,0xbbd9b61f,0x323eb9a8,0x3aa73b64,0xb872bc00,0x3bd9361f,0xb23e39a8,0xbaa7bb64,0xbaa70000,0xb23ebb64,0x3bd939a8,0xb872361f,
0xb61fbc00,0x3b6439a8,0xbb640000,0x361fb9a8,0x361f3c00,0xbb64b9a8,0x3b648000,0xb61f39a8,0x3b648000,0xb61f39a8,0xb61fbc00,0x3b6439a8,0xbb640000,0x361fb9a8,0x361f3c00,0xbb64b9a8,
0x39a80000,0x39a83c00,0xb9a80000,0xb9a8bc00,0x39a88000,0x39a83c00,0xb9a80000,0xb9a8bc00,0x39a83c00,0xb9a80000,0xb9a8bc00,0x39a88000,0x39a83c00,0xb9a80000,0xb9a8bc00,0x39a88000,
0x3aa70000,0x323e3b64,0xbbd9b9a8,0x3872b61f,0x38723c00,0xbbd9b61f,0x323eb9a8,0x3aa73b64,0x38723c00,0xbbd9b61f,0x323eb9a8,0x3aa73b64,0xbaa70000,0xb23ebb64,0x3bd939a8,0xb872361f,
0xbb640000,0x361fb9a8,0x361f3c00,0xbb64b9a8,0x3b640000,0xb61f39a8,0xb61fbc00,0x3b6439a8,0xb61fbc00,0x3b6439a8,0xbb640000,0x361fb9a8,0x361f3c00,0xbb64b9a8,0x3b648000,0xb61f39a8,
0xb23ebc00,0x38723b64,0xbaa7b9a8,0x3bd9361f,0x3bd90000,0xbaa7361f,0x3872b9a8,0xb23e3b64,0x3bd98000,0xbaa7361f,0x3872b9a8,0xb23e3b64,0x323e3c00,0xb872bb64,0x3aa739a8,0xbbd9b61f,
0xb9a83c00,0x39a88000,0x39a8bc00,0xb9a80000,0xb9a83c00,0x39a88000,0x39a8bc00,0xb9a88000,0x39a80000,0x39a8bc00,0xb9a80000,0xb9a83c00,0x39a88000,0x39a8bc00,0xb9a80000,0xb9a83c00,
0xbaa73c00,0x323e361f,0x3bd9b9a8,0x3872bb64,0xb8728000,0xbbd93b64,0xb23e39a8,0x3aa7b61f,0x38720000,0x3bd9bb64,0x323eb9a8,0xbaa7361f,0xbaa73c00,0x323e361f,0x3bd9b9a8,0x3872bb64,
0x3b64bc00,0x361fb9a8,0xb61f8000,0xbb6439a8,0xbb643c00,0xb61f39a8,0x361f8000,0x3b64b9a8,0xb61f0000,0xbb6439a8,0xbb643c00,0xb61f39a8,0x361f0000,0x3b64b9a8,0x3b64bc00,0x361fb9a8,
0x323e8000,0x3872b61f,0x3aa7b9a8,0x3bd9bb64,0xbbd93c00,0xbaa73b64,0xb87239a8,0xb23e361f,0x3bd9bc00,0x3aa7bb64,0x3872b9a8,0x323eb61f,0x323e0000,0x3872b61f,0x3aa7b9a8,0x3bd9bb64,
0xbaa70000,0xb23e3b64,0x3bd9b9a8,0xb872b61f,0xb8723c00,0x3bd9b61f,0xb23eb9a8,0xbaa73b64,0xb8723c00,0x3bd9b61f,0xb23eb9a8,0xbaa73b64,0x3aa78000,0x323ebb64,0xbbd939a8,0x3872361f,
0xb9a80000,0xb9a83c00,0x39a80000,0x39a8bc00,0xb9a88000,0xb9a83c00,0x39a80000,0x39a8bc00,0xb9a83c00,0x39a80000,0x39a8bc00,0xb9a88000,0xb9a83c00,0x39a88000,0x39a8bc00,0xb9a88000,
0x323ebc00,0xb8723b64,0x3aa7b9a8,0xbbd9361f,0xbbd90000,0x3aa7361f,0xb872b9a8,0x323e3b64,0xbbd98000,0x3aa7361f,0xb872b9a8,0x323e3b64,0xb23e3c00,0x3872bb64,0xbaa739a8,0x3bd9b61f,
0x3b640000,0xb61fb9a8,0xb61f3c00,0x3b64b9a8,0xbb640000,0x361f39a8,0x361fbc00,0xbb6439a8,0x361fbc00,0xbb6439a8,0x3b640000,0xb61fb9a8,0xb61f3c00,0x3b64b9a8,0xbb648000,0x361f39a8,
0x3aa73c00,0xb23e361f,0xbbd9b9a8,0xb872bb64,0x38728000,0x3bd93b64,0x323e39a8,0xbaa7b61f,0xb8720000,0xbbd9bb64,0xb23eb9a8,0x3aa7361f,0x3aa73c00,0xb23e361f,0xbbd9b9a8,0xb872bb64,
0x39a83c00,0xb9a88000,0xb9a8bc00,0x39a88000,0x39a83c00,0xb9a88000,0xb9a8bc00,0x39a80000,0xb9a80000,0xb9a8bc00,0x39a80000,0x39a83c00,0xb9a88000,0xb9a8bc00,0x39a88000,0x39a83c00,
0xb23e8000,0xb872b61f,0xbaa7b9a8,0xbbd9bb64,0x3bd93c00,0x3aa73b64,0x387239a8,0x323e361f,0xbbd9bc00,0xbaa7bb64,0xb872b9a8,0xb23eb61f,0xb23e0000,0xb872b61f,0xbaa7b9a8,0xbbd9bb64,
0xbb64bc00,0xb61fb9a8,0x361f0000,0x3b6439a8,0x3b643c00,0x361f39a8,0xb61f8000,0xbb64b9a8,0x361f0000,0x3b6439a8,0x3b643c00,0x361f39a8,0xb61f0000,0xbb64b9a8,0xbb64bc00,0xb61fb9a8,
};
__device__ __align__(1024) bf16 g_x1T[DM * XP];
__device__ __align__(1024) bf16 g_x2T[2][DM * XP];
__device__ __align__(1024) float g_sums[2][2][SEQ];

#define TS_SMEM 0
#define TS_DECL
#define TS_ARG
#define TS_PASS
#define TS_PHASE(p)
#define TS(i)
#define TSX(row, i)
#define TS_BEGIN
#define TS_END

__device__ __align__(1024) uint32_t g_keo[128][3][2048];

struct cplx { float r, i; };
__device__ __forceinline__ cplx cmul(cplx a, cplx b) {
    cplx o;
    o.r = fmaf(a.r, b.r, -a.i * b.i);
    o.i = fmaf(a.r, b.i, a.i * b.r);
    return o;
}
__device__ __forceinline__ cplx csq(cplx a) {
    cplx o;
    o.r = fmaf(a.r, a.r, -a.i * a.i);
    o.i = 2.f * a.r * a.i;
    return o;
}
__device__ __forceinline__ cplx cexp_p(float arl, float ai, float p) {
    float mag = ex2(arl * p);
    float ang = ai * p;
    float n = rintf(ang * 0.15915494309189535f);
    float r = fmaf(n, -6.2831854820251465f, ang);
    r = fmaf(n, 1.7484555e-7f, r);
    cplx o;
    o.r = mag * __cosf(r);
    o.i = mag * __sinf(r);
    return o;
}

__device__ __forceinline__ uint32_t pack2h(float lo, float hi) {
    uint32_t r;
    asm("cvt.rn.f16x2.f32 %0, %1, %2;" : "=r"(r) : "f"(hi), "f"(lo));
    return r;
}
__device__ __forceinline__ uint32_t hmul(uint32_t a, uint32_t b) { uint32_t d; asm("mul.rn.f16x2 %0, %1, %2;" : "=r"(d) : "r"(a), "r"(b)); return d; }
__device__ __forceinline__ uint32_t hfma(uint32_t a, uint32_t b, uint32_t c) { uint32_t d; asm("fma.rn.f16x2 %0, %1, %2, %3;" : "=r"(d) : "r"(a), "r"(b), "r"(c)); return d; }
__device__ __forceinline__ uint32_t hfms(uint32_t a, uint32_t b, uint32_t c) {
    uint32_t d;
    asm("{\n.reg .b32 n;\nneg.f16x2 n, %1;\nfma.rn.f16x2 %0, n, %2, %3;\n}" : "=r"(d) : "r"(a), "r"(b), "r"(c));
    return d;
}
__device__ __forceinline__ uint32_t hadd(uint32_t a, uint32_t b) { uint32_t d; asm("add.rn.f16x2 %0, %1, %2;" : "=r"(d) : "r"(a), "r"(b)); return d; }
__device__ __forceinline__ uint32_t hsub(uint32_t a, uint32_t b) { uint32_t d; asm("sub.rn.f16x2 %0, %1, %2;" : "=r"(d) : "r"(a), "r"(b)); return d; }
__device__ __forceinline__ uint4 ldg_tab(int tab, int t) {
    uint4 v;
    asm volatile("ld.global.nc.v4.u32 {%0,%1,%2,%3}, [%4];" : "=r"(v.x), "=r"(v.y), "=r"(v.z), "=r"(v.w) : "l"((const uint4*)c_fft + tab * 128 + t));
    return v;
}
__device__ __forceinline__ uint32_t u4(const uint4& v, int i) { return i == 0 ? v.x : i == 1 ? v.y : i == 2 ? v.z : v.w; }
struct cpair { uint32_t r, i; };
__device__ __forceinline__ cpair pmul(cpair p, uint32_t z) {
    const __half2 zv = *reinterpret_cast<const __half2*>(&z), pr = *reinterpret_cast<const __half2*>(&p.r), pi = *reinterpret_cast<const __half2*>(&p.i);
    const __half2 zr = __low2half2(zv), zi = __high2half2(zv);
    const __half2 a = __hfma2(__hneg2(pi), zi, __hmul2(pr, zr)), b = __hfma2(pi, zr, __hmul2(pr, zi));
    return {*reinterpret_cast<const uint32_t*>(&a), *reinterpret_cast<const uint32_t*>(&b)};
}
__device__ __forceinline__ uint32_t packz(cplx z) { return pack2h(z.r, z.i); }
__device__ __forceinline__ void wgmma_kg(float (&d)[24], uint64_t da, uint64_t db, int scale_d) {
    asm volatile("{\n.reg .pred p;\nsetp.ne.b32 p, %26, 0;\n"
                 "wgmma.mma_async.sync.aligned.m64n48k16.f32.f16.f16 "
                 "{%0,%1,%2,%3,%4,%5,%6,%7,%8,%9,%10,%11,%12,%13,%14,%15,%16,%17,%18,%19,%20,%21,%22,%23}, %24, %25, p, 1, 1, 1, 1;\n}\n"
                 : "+f"(d[0]), "+f"(d[1]), "+f"(d[2]), "+f"(d[3]), "+f"(d[4]), "+f"(d[5]), "+f"(d[6]), "+f"(d[7]), "+f"(d[8]), "+f"(d[9]),
                   "+f"(d[10]), "+f"(d[11]), "+f"(d[12]), "+f"(d[13]), "+f"(d[14]), "+f"(d[15]), "+f"(d[16]), "+f"(d[17]), "+f"(d[18]), "+f"(d[19]),
                   "+f"(d[20]), "+f"(d[21]), "+f"(d[22]), "+f"(d[23])
                 : "l"(da), "l"(db), "r"(scale_d));
}

struct SsmParams { const bf16 *lar, *aim, *cre, *cim, *logdt, *dskip; };
constexpr int KG_TABLES = 6 * 16384, KG_RES = 3136, KG_IDX = 6 * KG_RES, KG_DUMP = KG_IDX + 4096;
struct KgShared { uint32_t kmax[6], kexp[5]; float cinv[6]; };
struct KgParams { uint32_t l[3], a[3], r[3], i[3], dt, ds; };

__device__ __forceinline__ bool kg_is_hi(int warp) { return ((warp >> 1) ^ (warp >> 2)) & 1; }
__device__ __forceinline__ void kgen_load(KgParams& kp, int d0, int warp, int lane, const SsmParams& sp) {
    const int d = d0 + min(2 * (warp >> 2) + (warp & 1), 4), idx = d * (NMODE / 2) + lane;
    const bf16 *pr = kg_is_hi(warp) ? sp.cre : sp.lar, *pi = kg_is_hi(warp) ? sp.cim : sp.aim;
    kp.dt = __ldg((const uint16_t*)sp.logdt + d);
#pragma unroll
    for (int j = 0; j < 3; j++) {
        kp.l[j] = __ldg((const uint32_t*)sp.lar + idx + 32 * j); kp.a[j] = __ldg((const uint32_t*)sp.aim + idx + 32 * j);
        kp.r[j] = __ldg((const uint32_t*)pr + idx + 32 * j); kp.i[j] = __ldg((const uint32_t*)pi + idx + 32 * j);
    }
    kp.ds = __ldg((const uint16_t*)sp.dskip + d0 + min(warp >> 1, 4));
}

struct KgAnchors { uint32_t v[8]; };
__device__ __forceinline__ KgAnchors kg_anchor_lo(const KgParams& kp, uint32_t sel, float dt) {
    auto B = [&](uint32_t v) { return __uint_as_float(__byte_perm(v, 0u, sel)); };
    const float arl = -rbf(ex2(B(kp.l[0]) * 1.4426950408889634f)) * dt * 1.4426950408889634f, ai = B(kp.a[0]) * dt;
    const cplx z8 = cexp_p(arl, ai, 8.f), z16 = csq(z8), z24 = cmul(z16, z8), z32 = csq(z16), z64 = csq(z32), z128 = csq(z64), z192 = cmul(z128, z64);
    return {{pack2h(1.f, z8.r), pack2h(0.f, z8.i), pack2h(z16.r, z24.r), pack2h(z16.i, z24.i), packz(z32), packz(z64), packz(z128), packz(z192)}};
}
__device__ __forceinline__ KgAnchors kg_anchor_hi(const KgParams& kp, uint32_t sel, float dt, float cs) {
    auto B = [&](uint32_t v) { return __uint_as_float(__byte_perm(v, 0u, sel)); };
    const float arl = -rbf(ex2(B(kp.l[0]) * 1.4426950408889634f)) * dt * 1.4426950408889634f, ai = B(kp.a[0]) * dt;
    const cplx z1 = cexp_p(arl, -ai, 1.f), z2 = csq(z1), z4 = csq(z2), z256 = cexp_p(arl, -ai, 256.f), z512 = csq(z256), z1024 = csq(z512);
    const cplx H0 = {B(kp.r[0]) * cs, -B(kp.i[0]) * cs}, H4 = cmul(H0, z4);
    return {{pack2h(H0.r, H4.r), pack2h(H0.i, H4.i), packz(z1), packz(z2), packz(z256), packz(z512), packz(z1024), 0u}};
}

__device__ __forceinline__ void kgen_tables(KgParams& kp, uint32_t scr, uint32_t dump, KgShared* ks, int warp, int lane TS_ARG) {
    const int wg = warp >> 2, half = warp & 1, sw = lane & 7;
    const bool hi = kg_is_hi(warp);
    TS(23);
    const float dt = rbf(ex2(bf_lo(kp.dt) * 1.4426950408889634f));
    uint32_t sel = (wg == 2 && half) ? 0x3244u : 0x1044u;
    float cs = 0.f;
    KgAnchors an;
    if (hi) {
        uint32_t m = 0;
#pragma unroll
        for (int j = 0; j < 3; j++) m = __vmaxu2(m, __vmaxu2(kp.r[j] & 0x7FFF7FFFu, kp.i[j] & 0x7FFF7FFFu));
        m = __reduce_max_sync(~0u, max(m << 16, m & 0xFFFF0000u));
        const uint32_t e = min(max(__float_as_uint(2.f * dt * __uint_as_float(m)) >> 23, 2u), 252u);
        cs = 2.f * dt * __uint_as_float((253u - e) << 23);
        if (lane == 0) { ks->cinv[2 * wg + half] = __uint_as_float((e + 1u) << 23); ks->kmax[2 * wg + half] = 0u; }
        an = kg_anchor_hi(kp, sel, dt, cs);
    } else {
        an = kg_anchor_lo(kp, sel, dt);
    }
    float acc[24];
#pragma unroll
    for (int i = 0; i < 24; i++) acc[i] = 0.f;
    uint32_t tb = scr + 2 * wg * 16384 + lane * 128;
    uint64_t da = mkdesc(scr + 2 * wg * 16384, 4096, 1024, 1);
    int flip = 16384;
#pragma unroll 1
    for (int c = wg == 2 ? 1 : 0, step = wg == 2 ? 2 : 1; c < 6; c += step) {
        if (wg < 2) sel ^= 0x2200u;
        if (!hi) {
            if (c & 1) { kp.l[0] = kp.l[1]; kp.l[1] = kp.l[2]; kp.a[0] = kp.a[1]; kp.a[1] = kp.a[2]; }
            cpair p[4];
            p[0] = {an.v[0], an.v[1]}; p[1] = {an.v[2], an.v[3]};
            p[2] = pmul(p[0], an.v[4]); p[3] = pmul(p[1], an.v[4]);
#pragma unroll
            for (int j = 0; j < 4; j++) {
                cpair v[4];
#pragma unroll
                for (int i = 0; i < 4; i++) v[i] = j ? pmul(p[i], an.v[4 + j]) : p[i];
                const uint32_t a = tb + (((4 * half + j) ^ sw) << 4);
                sts128(a, make_uint4(v[0].r, v[1].r, v[2].r, v[3].r));
                sts128(a + 4096, make_uint4(v[0].i, v[1].i, v[2].i, v[3].i));
            }
            an = kg_anchor_lo(kp, sel, dt);
        } else {
            if (c & 1) {
#pragma unroll
                for (int j = 0; j < 2; j++) { kp.l[j] = kp.l[j + 1]; kp.a[j] = kp.a[j + 1]; kp.r[j] = kp.r[j + 1]; kp.i[j] = kp.i[j + 1]; }
            }
            const uint32_t h1 = an.v[2], h2 = an.v[3], h256 = an.v[4], h512 = an.v[5], h1024 = an.v[6];
            cpair p[11];
            p[0] = {an.v[0], an.v[1]};
            p[1] = pmul(p[0], h2); p[2] = pmul(p[0], h1); p[3] = pmul(p[1], h1);
            p[4] = pmul(p[0], h256); p[5] = pmul(p[1], h256); p[6] = pmul(p[0], h512); p[7] = pmul(p[4], h512);
            p[8] = pmul({__byte_perm(p[0].r, p[4].r, 0x5410), __byte_perm(p[0].i, p[4].i, 0x5410)}, h1024);
            p[9] = pmul(p[8], h512); p[10] = pmul(p[8], h1024);
#pragma unroll
            for (int j = 0; j < 3; j++) {
                const uint32_t a = tb + 8192 + (((3 * half + j) ^ sw) << 4);
                sts128(a, make_uint4(p[4 * j].r, p[4 * j + 1].r, p[4 * j + 2].r, p[j < 2 ? 4 * j + 3 : 10].r));
                sts128(a + 4096, make_uint4(p[4 * j].i, p[4 * j + 1].i, p[4 * j + 2].i, p[j < 2 ? 4 * j + 3 : 10].i));
            }
            an = kg_anchor_hi(kp, sel, dt, cs);
        }
        if (c == 0) TS(24);
        if (c == 3) TS(25);
        fence_async_smem();
        wg_wait<0>();
        named_bar(5 + wg, 128);
        wg_fence();
#pragma unroll
        for (int k = 0; k < 4; k++) wgmma_kg(acc, da + k * 128, da + 512 + k * 128, 1);
        wg_commit();
        tb += flip; da += flip >> 4; flip = -flip;
    }
    const bool up = warp & 2;
    const int r = 2 * wg + up, lo0 = 16 * half + (lane >> 2);
    const uint32_t o = dump + r * KG_RES + (lo0 * 24 + 2 * (lo0 >> 2) + 2 * (lane & 3)) * 4;
    const float ci = __uint_as_float(lds32(s2u(&ks->cinv[r])));
    const float ds = (lane == 0 && warp <= 8 && !half) ? bf_lo(kp.ds) : 0.f;
    TS(26);
    wg_wait<0>();
    float m = 0.f;
#pragma unroll
    for (int j = 0; j < 3; j++)
#pragma unroll
        for (int h = 0; h < 2; h++) {
            const float v0 = fmaf(ci, up ? acc[12 + 4 * j + 2 * h] : acc[4 * j + 2 * h], j + h ? 0.f : ds), v1 = ci * (up ? acc[13 + 4 * j + 2 * h] : acc[4 * j + 2 * h + 1]);
            asm volatile("st.shared.v2.f32 [%0], {%1, %2};" ::"r"(o + h * 784 + j * 32), "f"(v0), "f"(v1) : "memory");
            m = fmaxf(m, fmaxf(fabsf(v0), fabsf(v1)));
        }
    const uint32_t mm = __reduce_max_sync(~0u, __float_as_uint(m));
    if (lane == 0) asm volatile("red.shared.max.u32 [%0], %1;" ::"r"(s2u(&ks->kmax[r])), "r"(mm) : "memory");
}

__device__ __forceinline__ void kgen_expand(int bx, uint32_t dump, KgShared* ks, int ht TS_ARG) {
    const int lane = ht & 31;
    auto F = [](uint32_t x) { return __uint_as_float(x); };
#pragma unroll 1
    for (int task = ht >> 5; task < 20; task += 3) {
        const int c = task >> 2, it = (task & 3) * 32 + lane, a = it >> 2;
        const uint4 o0 = lds128(dump + KG_IDX + it * 16), o1 = lds128(dump + KG_IDX + 2048 + it * 16);
        const uint32_t e = min(max(__float_as_uint(F(ks->kmax[c]) + (c == 4 ? F(ks->kmax[5]) : 0.f)) >> 23, 4u), 250u), b = dump + c * KG_RES;
        const float sc = __uint_as_float((253u - e) << 23);
        if (it == 0) ks->kexp[c] = e;
        float x[16];
#pragma unroll
        for (int i = 0; i < 8; i++) {
            const uint32_t w = u4(i < 4 ? o0 : o1, i & 3);
            x[2 * i] = F(lds32(b + (w & 0xFFFF))); x[2 * i + 1] = F(lds32(b + (w >> 16)));
        }
        if (c == 4) {
#pragma unroll
            for (int i = 0; i < 8; i++) {
                const uint32_t w = u4(i < 4 ? o0 : o1, i & 3);
                x[2 * i] += F(lds32(b + KG_RES + (w & 0xFFFF))); x[2 * i + 1] += F(lds32(b + KG_RES + (w >> 16)));
            }
        }
        uint32_t ev[4], ov[4];
#pragma unroll
        for (int i = 0; i < 4; i++) {
            ev[i] = pack2h((x[2 * i] + x[8 + 2 * i]) * sc, (x[2 * i + 1] + x[9 + 2 * i]) * sc);
            ov[i] = pack2h((x[2 * i] - x[8 + 2 * i]) * sc, (x[2 * i + 1] - x[9 + 2 * i]) * sc);
        }
        uint32_t* dst = &g_keo[bx][c >> 1][a * 32 + (((4 * (c & 1) + (it & 3)) ^ (a & 7)) << 2)];
        stg128(dst, make_uint4(ev[0], ev[1], ev[2], ev[3]));
        stg128(dst + 1024, make_uint4(ov[0], ov[1], ov[2], ov[3]));
    }
}
#define F_WEAK 0
#define F_STAG 0
#define F_SHARE 0
__device__ __forceinline__ void wgmma_h64_rs(uint32_t (&d)[16], const uint4& a, uint64_t db, int scale_d) {
    asm volatile("{\n.reg .pred p;\nsetp.ne.b32 p, %21, 0;\n"
                 "wgmma.mma_async.sync.aligned.m64n64k16.f16.f16.f16 {%0,%1,%2,%3,%4,%5,%6,%7,%8,%9,%10,%11,%12,%13,%14,%15}, {%16,%17,%18,%19}, %20, p, 1, 1, 1;\n}\n"
                 : "+r"(d[0]), "+r"(d[1]), "+r"(d[2]), "+r"(d[3]), "+r"(d[4]), "+r"(d[5]), "+r"(d[6]), "+r"(d[7]), "+r"(d[8]), "+r"(d[9]),
                   "+r"(d[10]), "+r"(d[11]), "+r"(d[12]), "+r"(d[13]), "+r"(d[14]), "+r"(d[15])
                 : "r"(a.x), "r"(a.y), "r"(a.z), "r"(a.w), "l"(db), "r"(scale_d));
}
template <int TB>
__device__ __forceinline__ void wgmma_h32_rs(uint32_t (&d)[8], const uint4& a, uint64_t db, int scale_d) {
    asm volatile("{\n.reg .pred p;\nsetp.ne.b32 p, %13, 0;\n"
                 "wgmma.mma_async.sync.aligned.m64n32k16.f16.f16.f16 {%0,%1,%2,%3,%4,%5,%6,%7}, {%8,%9,%10,%11}, %12, p, 1, 1, %14;\n}\n"
                 : "+r"(d[0]), "+r"(d[1]), "+r"(d[2]), "+r"(d[3]), "+r"(d[4]), "+r"(d[5]), "+r"(d[6]), "+r"(d[7])
                 : "r"(a.x), "r"(a.y), "r"(a.z), "r"(a.w), "l"(db), "r"(scale_d), "n"(TB));
}
__device__ __forceinline__ void wgmma_s1(uint32_t (&d)[16], const uint4& a, uint64_t db, int scale_d) { wgmma_h64_rs(d, a, db, scale_d); }
__device__ __forceinline__ void wgmma_s1(uint32_t (&d)[8], const uint4& a, uint64_t db, int scale_d) { wgmma_h32_rs<1>(d, a, db, scale_d); }
__device__ __forceinline__ void wgmma_s4(float (&d)[32], const uint4& a, uint64_t db, uint32_t meta, int scale_d) {
    asm volatile("{\n.reg .pred p;\nsetp.ne.b32 p, %38, 0;\n"
                 "wgmma.mma_async.sp.sync.aligned.m64n64k32.f32.f16.f16 {%0,%1,%2,%3,%4,%5,%6,%7,%8,%9,%10,%11,%12,%13,%14,%15,%16,%17,%18,%19,%20,%21,%22,%23,%24,%25,%26,%27,%28,%29,%30,%31}, {%32,%33,%34,%35}, %36, %37, 0, p, 1, 1, 1;\n}\n"
                 : "+f"(d[0]), "+f"(d[1]), "+f"(d[2]), "+f"(d[3]), "+f"(d[4]), "+f"(d[5]), "+f"(d[6]), "+f"(d[7]), "+f"(d[8]), "+f"(d[9]), "+f"(d[10]), "+f"(d[11]), "+f"(d[12]), "+f"(d[13]), "+f"(d[14]), "+f"(d[15]), "+f"(d[16]), "+f"(d[17]), "+f"(d[18]), "+f"(d[19]), "+f"(d[20]), "+f"(d[21]), "+f"(d[22]), "+f"(d[23]), "+f"(d[24]), "+f"(d[25]), "+f"(d[26]), "+f"(d[27]), "+f"(d[28]), "+f"(d[29]), "+f"(d[30]), "+f"(d[31])
                 : "r"(a.x), "r"(a.y), "r"(a.z), "r"(a.w), "l"(db), "r"(meta), "r"(scale_d));
}
__device__ __forceinline__ void wgmma_s4(float (&d)[16], const uint4& a, uint64_t db, uint32_t meta, int scale_d) {
    asm volatile("{\n.reg .pred p;\nsetp.ne.b32 p, %22, 0;\n"
                 "wgmma.mma_async.sp.sync.aligned.m64n32k32.f32.f16.f16 {%0,%1,%2,%3,%4,%5,%6,%7,%8,%9,%10,%11,%12,%13,%14,%15}, {%16,%17,%18,%19}, %20, %21, 0, p, 1, 1, 1;\n}\n"
                 : "+f"(d[0]), "+f"(d[1]), "+f"(d[2]), "+f"(d[3]), "+f"(d[4]), "+f"(d[5]), "+f"(d[6]), "+f"(d[7]), "+f"(d[8]), "+f"(d[9]), "+f"(d[10]), "+f"(d[11]), "+f"(d[12]), "+f"(d[13]), "+f"(d[14]), "+f"(d[15])
                 : "r"(a.x), "r"(a.y), "r"(a.z), "r"(a.w), "l"(db), "r"(meta), "r"(scale_d));
}

__device__ __forceinline__ uint32_t& u4r(uint4& v, int i) { return i == 0 ? v.x : i == 1 ? v.y : i == 2 ? v.z : v.w; }

template <int NC, bool SHEAR, class Mid>
__device__ __forceinline__ void fft_forward(const uint4 (&a1)[4], const uint4 (&tw)[4], uint32_t eo, uint32_t s2, uint32_t (&X)[NC][2][8], Mid mid) {
    uint32_t dr[8 * NC], di[8 * NC];
    const uint64_t de = mkdesc(eo, 4096, 1024, 1), d2 = mkdesc(s2, 16, 1024, 1);
    wg_fence();
    wgmma_s1(dr, a1[0], de, 0);
    wgmma_s1(di, a1[2], de + 256, 0);
    wgmma_s1(dr, a1[1], de + 128, 1);
    wgmma_s1(di, a1[3], de + 384, 1);
    wg_commit();
    mid();
    wg_wait<0>();
#pragma unroll
    for (int c = 0; c < NC; c++) {
        uint4 zr[2], zi[2];
#pragma unroll
        for (int p = 0; p < 2; p++)
#pragma unroll
            for (int i = 0; i < 4; i++) {
                const uint32_t r = dr[8 * c + 4 * p + i], m = di[8 * c + 4 * p + i], tr = u4(tw[p], i), ti = u4(tw[2 + p], i);
                if (SHEAR) {
                    const uint32_t r1 = hfma(tr, m, r), m1 = hfma(ti, r1, m);
                    u4r(zr[p], i) = hfma(tr, m1, r1); u4r(zi[p], i) = m1;
                } else {
                    u4r(zr[p], i) = hfms(m, ti, hmul(r, tr));
                    u4r(zi[p], i) = hfma(m, tr, hmul(r, ti));
                }
            }
        wg_fence();
        wgmma_h32_rs<0>(X[c][0], zi[0], d2 + 2, 0);
        wgmma_h32_rs<0>(X[c][1], zi[1], d2 + 6, 0);
        wgmma_h32_rs<0>(X[c][0], zr[0], d2, 1);
        wgmma_h32_rs<0>(X[c][1], zr[1], d2 + 4, 1);
        wg_commit();
    }
}

template <int NC, class Mid, class Ready, class Asked, class Staged>
__device__ __forceinline__ void conv_wg(int ch0, int layer, uint32_t eo, uint32_t zb, uint32_t s23, uint32_t kbar, uint32_t kexp, uint32_t st, uint32_t sbar,
                                        int warp, int lane, uint4 (&a1)[4], uint4 (&tw)[4], Mid mid, Ready ready, Asked asked, Staged staged TS_ARG) {
    const int wg = warp >> 2, w = warp & 3, t = 32 * w + lane, g = lane >> 2, q = lane & 3, mi = lane >> 3, mj = lane & 7;
    auto F = [](uint32_t x) { return __uint_as_float(x); };
    auto U = [](float x) { return __float_as_uint(x); };
    uint32_t KH[NC][2][8];
    TS(1);
    mbar_wait(kbar, 0);
    TS(2);
    fft_forward<NC, false>(a1, tw, eo, s23, KH, mid);
    named_bar(1 + wg, 128);
    uint4 a4[4];
    if (NC == 2) {
#pragma unroll
        for (int i = 0; i < 4; i++) { tw[i] = ldg_tab(4 + i, t); a4[i] = ldg_tab(12 + i, t); }
    }
    wg_wait<0>();
    TS(4);
    ready();
    TS(5);
    uint2 x[NC][2][2];
    const int ra[2] = {16 * (8 * w + g) + 4 * q, 16 * (63 - 8 * w - g) + 4 * q};
    {
        uint4 s[2][2][2];
        constexpr bool own = NC == 1 || !F_SHARE;
#pragma unroll
        for (int h = 0; h < 2; h++)
#pragma unroll
            for (int p = 0; p < 2; p++) {
                if (own) { s[h][p][0] = ldg128(g_sums[layer][0] + 1024 * p + ra[h]); s[h][p][1] = ldg128(g_sums[layer][1] + 1024 * p + ra[h]); }
                if (NC == 2) {
#pragma unroll
                    for (int c = 0; c < NC; c++) x[c][h][p] = ldg64(g_x1T + (size_t)(ch0 + c) * XP + 1024 * p + ra[h]);
                }
            }
        asked();
        if (NC == 1) {
#pragma unroll
            for (int i = 0; i < 4; i++) x[0][i >> 1][i & 1] = ldg64(g_x1T + (size_t)ch0 * XP + 1024 * (i & 1) + ra[i >> 1]);
        }
        TS(6);
        if (own) {
#pragma unroll
            for (int hp = 0; hp < 4; hp++) {
                uint4 &a = s[hp >> 1][hp & 1][0], &b = s[hp >> 1][hp & 1][1];
#pragma unroll
                for (int i = 0; i < 4; i++) {
                    const float m = F(u4(a, i)) * (1.0f / DM), r = frsq(fmaxf(fmaf(F(u4(b, i)), 1.0f / DM, fmaf(-m, m, 1e-5f)), 1e-5f));
                    u4r(a, i) = U(r); u4r(b, i) = U(-m * r);
                }
                if (F_SHARE) { sts128(st + (2 * hp) * 2048 + t * 16, a); sts128(st + (2 * hp + 1) * 2048 + t * 16, b); }
            }
            if (F_SHARE) { __syncwarp(); if (lane == 0) mbar_arrive(sbar + 8 * w); }
        } else {
            mbar_wait(sbar + 8 * w, 0);
#pragma unroll
            for (int i = 0; i < 8; i++) s[i >> 2][(i >> 1) & 1][i & 1] = lds128(st + i * 2048 + t * 16);
        }
        if (F_STAG == 1 && NC == 2 && wg == 1) named_bar(10 + w, 64);
        TS(7);
#pragma unroll
        for (int c = 0; c < NC; c++) {
            uint32_t u[2][4];
#pragma unroll
            for (int h = 0; h < 2; h++)
#pragma unroll
                for (int j = 0; j < 4; j++) {
                    const uint4 &a = s[h][j >> 1][0], &b = s[h][j >> 1][1];
                    const uint32_t xv = (j & 1) ? x[c][h][j >> 1].y : x[c][h][j >> 1].x;
                    u[h][j] = pack2h(fmaf(bf_lo(xv), F(u4(a, 2 * (j & 1))), F(u4(b, 2 * (j & 1)))), fmaf(bf_hi(xv), F(u4(a, 2 * (j & 1) + 1)), F(u4(b, 2 * (j & 1) + 1))));
                }
            const uint32_t a = eo + (8 * w + mj) * 128 + (((4 * c + mi) ^ mj) << 4);
            stsm_x4(a, hadd(u[0][0], u[1][0]), hadd(u[0][1], u[1][1]), hadd(u[0][2], u[1][2]), hadd(u[0][3], u[1][3]));
            stsm_x4(a + 4096, hsub(u[0][0], u[1][0]), hsub(u[0][1], u[1][1]), hsub(u[0][2], u[1][2]), hsub(u[0][3], u[1][3]));
        }
    }
    if (F_STAG == 1 && NC == 2 && wg == 0) asm volatile("bar.arrive %0, 64;" ::"r"(10 + w) : "memory");
    TS(8);
    fence_async_smem();
    TS(9);
    if (NC == 1) {
#pragma unroll
        for (int i = 0; i < 4; i++) { tw[i] = ldg_tab(4 + i, t); a4[i] = ldg_tab(12 + i, t); }
    }
    staged();
    named_bar(1 + wg, 128);
    uint32_t X[NC][2][8], Y[NC][2][8];
    fft_forward<NC, true>(a1, tw, eo, s23, X, [&] { TS(3); if (F_STAG >= 2 && NC == 2 && wg == 1) named_bar(10 + w, 64); });
    if (F_STAG == 2 && NC == 2 && wg == 0) asm volatile("bar.arrive %0, 64;" ::"r"(10 + w) : "memory");
    TS(10);
    const uint64_t d3 = mkdesc(s23 + 4096, 16, 1024, 1);
#pragma unroll
    for (int c = 0; c < NC; c++) {
        wg_wait<NC - 1>();
        TS(11 + c);
        uint4 pr[2], pi[2];
#pragma unroll
        for (int i = 0; i < 4; i++) {
            const uint32_t er = X[c][0][i], ei = X[c][0][4 + i], orr = X[c][1][i], oi = X[c][1][4 + i];
            const uint32_t ar = KH[c][0][i], ai = KH[c][0][4 + i], br = KH[c][1][i], bi = KH[c][1][4 + i];
            u4r(pr[0], i) = hfms(bi, oi, hfma(br, orr, hfms(ai, ei, hmul(ar, er))));
            u4r(pi[0], i) = hfma(bi, orr, hfma(br, oi, hfma(ai, er, hmul(ar, ei))));
            u4r(pr[1], i) = hfms(ai, oi, hfma(ar, orr, hfms(bi, ei, hmul(br, er))));
            u4r(pi[1], i) = hfma(ai, orr, hfma(ar, oi, hfma(bi, er, hmul(br, ei))));
        }
        if (F_STAG == 3 + c && NC == 2 && wg == 0) asm volatile("bar.arrive %0, 64;" ::"r"(10 + w), "r"(pr[0].x ^ pr[1].w ^ pi[0].y ^ pi[1].z) : "memory");
        wg_fence();
        wgmma_h32_rs<0>(Y[c][0], pr[0], d3, 0);
        wgmma_h32_rs<0>(Y[c][1], pr[1], d3 + 4, 0);
        wgmma_h32_rs<0>(Y[c][0], pi[0], d3 + 2, 1);
        wgmma_h32_rs<0>(Y[c][1], pi[1], d3 + 6, 1);
        wg_commit();
    }
#pragma unroll
    for (int c = 0; c < NC; c++) {
        if (c + 1 < NC) wg_wait<1>(); else wg_wait<0>();
        TS(13 + c);
        uint32_t zr[2][4], zi[2][4];
#pragma unroll
        for (int p = 0; p < 2; p++)
#pragma unroll
            for (int i = 0; i < 4; i++) {
                const uint32_t r = Y[c][p][i], m = Y[c][p][4 + i], tr = u4(tw[p], i), ti = u4(tw[2 + p], i);
                const uint32_t r1 = hfms(tr, m, r), m1 = hfms(ti, r1, m);
                zr[i & 1][2 * p + (i >> 1)] = hfms(tr, m1, r1);
                zi[i & 1][2 * p + (i >> 1)] = m1;
            }
        const int kr = 4 * (mj >> 1) + (mj & 1) + 2 * (mj >> 2), ki = kr ^ 2;
#pragma unroll
        for (int h = 0; h < 2; h++) {
            const uint32_t a = zb + (2 * w + h) * 2048;
            stsm_x4(a + ki * 128 + (((4 * c + mi) ^ (ki & 7)) << 4), zi[h][0], zi[h][1], zi[h][2], zi[h][3]);
            stsm_x4(a + kr * 128 + (((4 * c + mi) ^ (kr & 7)) << 4), zr[h][0], zr[h][1], zr[h][2], zr[h][3]);
        }
    }
    TS(15);
    fence_async_smem();
    TS(16);
    named_bar(1 + wg, 128);
    TS(17);
    float acc[16 * NC];
    const uint64_t dz = mkdesc(zb, 4096, 1024, 1);
    wg_fence();
#pragma unroll
    for (int ks = 0; ks < 4; ks++) wgmma_s4(acc, a4[ks], dz + ks * 256, 0x44EEEE44u, ks > 0);
    wg_commit();
    uint32_t oscale[NC];
#pragma unroll
    for (int c = 0; c < NC; c++) oscale[c] = (lds32(kexp + 4 * c) + 3u) * 0x00800080u;
    bf16* dst = g_x2T[layer] + (size_t)ch0 * XP;
    wg_wait<0>();
    TS(18);
#pragma unroll
    for (int c = 0; c < NC; c++)
#pragma unroll
        for (int p = 0; p < 2; p++) {
            uint32_t r[2][2];
#pragma unroll
            for (int j = 0; j < 2; j++) {
                const float* d = acc + 4 * (4 * c + 2 * p + j);
                const uint32_t y0 = pack2(d[0] + d[2], d[1] + d[3]), y1 = pack2(d[0] - d[2], d[1] - d[3]);
                asm("fma.rn.bf16x2 %0, %1, %2, %3;" : "=r"(r[0][j]) : "r"(y0), "r"(oscale[c]), "r"(j ? x[c][0][p].y : x[c][0][p].x));
                asm("fma.rn.bf16x2 %0, %1, %2, %3;" : "=r"(r[1][j]) : "r"(y1), "r"(oscale[c]), "r"(j ? x[c][1][p].y : x[c][1][p].x));
            }
#pragma unroll
            for (int h = 0; h < 2; h++)
                if (F_WEAK) *(uint2*)(dst + c * XP + 1024 * p + ra[h]) = make_uint2(r[h][0] ? r[h][0] : 0x80000000u, r[h][1]);
                else st_ll((unsigned long long*)(dst + c * XP + 1024 * p + ra[h]), r[h][0] ? r[h][0] : 0x80000000u, r[h][1]);
        }
    TS(19);
}

#define Q_SCHED 3
#define Q_WAITFOR(it) (Q_SCHED == 0 ? (it) - 2 : Q_SCHED == 1 ? ((it) == 3 ? 1 : 0) : Q_SCHED == 2 ? -1 : (it) - 1)
#define Q_S0 8
#define Q_WGATE 0
#define Q_ROT 0
#define O_ROT 0
#define K_EARLY 0
#define O_KAT 3
#define O_MASK 127u
#define O_DEPTH 3
#define O_GATE 0
#define A_HPOS 1
#define A_CSPRE 2
#define O_RING 1
#define R_CONS 200
#define F_PRE 4
#define FIN_DELAY 500
#define T_PF 1
#define K_CLR 0
#define K_CSUN 1
constexpr int K_CSU = K_CSUN;
#define FIN_SLEEP 0
constexpr int Q_ST = 4;
constexpr int Q_AB = 16384, Q_BB = 30720, Q_SB = Q_AB + Q_BB;
constexpr int Q_EROW = 336;
constexpr int Q_ESLOT = 8 * Q_EROW;
constexpr int Q_EOFF = Q_ST * Q_SB;
constexpr int Q_KG = 2 * Q_SB;
constexpr int Q_KDUMP = Q_EOFF + 16384;
static_assert(6 * Q_ESLOT <= 16384, "exchange slots");
static_assert(Q_KG + KG_TABLES <= Q_KDUMP, "kernel generation layout");
constexpr int Q_SMEM = Q_KDUMP + KG_DUMP + TS_SMEM;
constexpr int F_EO = Q_EOFF, F_S23 = F_EO + 3 * 8192;
static_assert(F_S23 + 8192 <= Q_SMEM, "convolution layout");
__host__ __device__ constexpr int w_grp(int j) { return j < 7 ? 2 * Q_SB + j * 12800 : 20480; }
constexpr int W_RES = 0, W_OUT = Q_SB;

constexpr int Q_ZERO = Q_EOFF + 4096, Q_WOT = Q_EOFF + 8320;

__device__ unsigned g_epoch;
__device__ __align__(1024) unsigned g_bar[4][16][32];
__device__ __align__(1024) uint4 g_wop[8][80][10][8];
__device__ __align__(1024) uint4 g_csp[8][16][96];
__device__ __align__(1024) uint4 g_stp[16][8][64];
__device__ __align__(1024) uint4 g_halo[128][2][5][32];
__device__ __align__(1024) uint4 g_of[8][16][8][5][32];

struct Bars { uint64_t full[Q_ST], empty[Q_ST], wfull[3], ex[7], res, go, qdone, att, prep, kf, ardy, hdone, fdone, idx, kdone, att1, kf2, st[4], kfree; };
constexpr int NBAR = sizeof(Bars) / 8;
__host__ __device__ constexpr int bar_count(int i) {
#define BAR_IS(f) (i == offsetof(Bars, f) / 8)
    return (i >= 4 && i < 8) ? 16 : (BAR_IS(go) || BAR_IS(att1) || BAR_IS(ardy)) ? 4 : (BAR_IS(qdone) || BAR_IS(att)) ? 8 : BAR_IS(prep) ? 96 :
           BAR_IS(hdone) ? 6 : BAR_IS(fdone) ? 3 : BAR_IS(kfree) ? 24 : 1;
}
__device__ __forceinline__ void grid_wait(const unsigned* c, int n, unsigned target, int lane) {
    const unsigned* p = c + 32 * min(lane, n - 1);
    unsigned v;
    int spin = 0;
    do { asm volatile("ld.relaxed.gpu.global.u32 %0, [%1];" : "=r"(v) : "l"(p) : "memory"); } while (!__all_sync(~0u, (int)(v - target) >= 0) && ++spin < (1 << 18));
    fence_acquire();
}
__device__ __forceinline__ void grid_arrive(unsigned* c) {
    fence_release();
    asm volatile("red.relaxed.gpu.global.add.u32 [%0], 1;" ::"l"(c) : "memory");
}

#define TMAP(n) ([] { const CUtensorMap* p_; asm volatile("{\n.reg .b64 t;\nmov.b64 t, fused_kernel_param_" #n ";\ncvta.param.u64 %0, t;\n}" : "=l"(p_)); return p_; }())
extern "C" __global__ void __launch_bounds__(384, 1)
fused_kernel(const SsmParams sp, const __grid_constant__ CUtensorMap mX0, const __grid_constant__ CUtensorMap mX1, const __grid_constant__ CUtensorMap mW,
             const __grid_constant__ CUtensorMap mWr,
             const __grid_constant__ CUtensorMap mRes0, const __grid_constant__ CUtensorMap mRes1, const __grid_constant__ CUtensorMap mOut,
             const __grid_constant__ CUtensorMap mWo, const __grid_constant__ CUtensorMap mFin) {
    extern __shared__ __align__(1024) char smraw[];
    __shared__ __align__(8) Bars s_bar[2];
    __shared__ __align__(16) float s_cs[240], s_mean[2][64], s_rstd[2][72];
    __shared__ KgShared s_kg;
    __shared__ uint32_t s_epoch;
    const uint32_t sb = s2u(smraw);
    int tid, warp, lane, bx, rank, blk, hg, rot, c0;
    auto indices = [&] {
        asm volatile("mov.u32 %0, %%tid.x;" : "=r"(tid));
        asm volatile("mov.u32 %0, %%ctaid.x;" : "=r"(bx));
        warp = __shfl_sync(~0u, tid >> 5, 0); lane = tid & 31;
        rank = bx & 1; blk = bx & 15; hg = bx >> 4;
        const int u = ((blk >> 1) + hg) & 7;
        rot = (5 * u) >> 2; c0 = 16 * (u & 3);
    };
    indices();
    TS_DECL;
    TS_BEGIN;
#define EPOCH lds32(s2u(&s_epoch))
    int layer = 0;
    uint32_t bars = s2u(s_bar);
#define BAR(f) (bars + (uint32_t)offsetof(Bars, f))
    auto chunk = [&](int it) { return Q_ROT ? it + rot - (it + rot >= 10 ? 10 : 0) : it < 2 ? rot + it : it - 2 < rot ? it - 2 : it; };
    auto osrc_of = [&](int j) { return O_ROT ? (hg + j) & 7 : j == 0 ? hg : j - 1 < hg ? j - 1 : j; };
    auto issue_w = [&](uint32_t bb, int it, int half) {
        const int s = it & (Q_ST - 1);
        const uint32_t fb = bb + 8 * s, db = sb + s * Q_SB + Q_AB + half * 15360;
        const int k0 = chunk(it) * 64 + half * 32;
#pragma unroll
        for (int p = 0; p < 3; p++) tma2d_mc(db + p * 4096, TMAP(3), p * DM + hg * 80, k0, fb, 3);
        tma3d_mc(db + 12288, TMAP(4), hg * 80 + 64, k0, 0, fb, 3);
    };
    auto issue_x = [&](int it) {
        const int s = it & (Q_ST - 1), kc = chunk(it);
        mbar_expect(BAR(full) + 8 * s, Q_SB);
        tma3d(sb + s * Q_SB, TMAP(1) + layer, (layer ? blk : kc) * 64, (layer ? kc : blk) * 64, 0, BAR(full) + 8 * s);
    };
    auto clear_fin = [&](uint32_t zero) {
#pragma unroll 1
        for (int i = 0; i < 5; i++) bulk_s2g(g_x2T[1] + (bx * 5 + i) * XP, zero, SEQ * 2);
        bulk_commit();
    };
    {
        KgParams kp;
        kgen_load(kp, bx * 5, warp, lane, sp);
        if (warp < 8) {
            cluster_arrive_relaxed();
        } else {
            const int t2 = tid - 256;
            if (elect_one()) {
                if (warp < 10) { prefetch_tmap(TMAP(3)); prefetch_tmap(TMAP(4)); } else prefetch_tmap(warp == 10 ? TMAP(1) : TMAP(8));
                const uint32_t b0 = bars + (warp >= 10 ? sizeof(Bars) : 0);
                if (warp & 1) {
#pragma unroll
                    for (int i = 0; i < NBAR / 2; i++) mbar_init(b0 + i * 8, bar_count(i));
                } else {
#pragma unroll
                    for (int i = NBAR / 2; i < NBAR; i++) mbar_init(b0 + i * 8, bar_count(i));
                }
                fence_mbar_init();
            }
            __syncwarp();
            cluster_arrive_relaxed();
            TS(29);
            const uint32_t epoch0 = ldg32(&g_epoch);
            sts128(sb + Q_ZERO + t2 * 16, make_uint4(0, 0, 0, 0)); sts128(sb + Q_ZERO + 2048 + t2 * 16, make_uint4(0, 0, 0, 0));
            cluster_wait();
            TS(27);
            if (elect_one()) {
                if (warp < 10) {
                    issue_w(BAR(full), warp - 8, rank);
                } else if (warp == 10) {
                    issue_x(0); issue_x(1);
                    prefetch_l2((const char*)c_fft + bx * (sizeof(c_fft) / 128), sizeof(c_fft) / 128);
                } else {
                    mbar_expect(BAR(idx), 4096 + 6400);
                    asm volatile("cp.async.bulk.tensor.4d.shared::cluster.global.mbarrier::complete_tx::bytes [%0], [%1, {0, 0, %3, %4}], [%2];"
                                 ::"r"(sb + Q_WOT), "l"(TMAP(8)), "r"(BAR(idx)), "r"(10 * hg), "r"(5 * blk) : "memory");
                    bulk_g2s(sb + Q_KDUMP + KG_IDX, c_fft + 16 * 512, 4096, BAR(idx));
                }
            }
            __syncwarp();
            if (t2 == 0) s_epoch = epoch0;
            TS(30);
        }
        indices();
        kgen_tables(kp, sb + Q_KG, sb + Q_KDUMP, &s_kg, warp, lane TS_PASS);
        if (warp < 8) cluster_wait();
        __syncwarp();
        if (lane == 0) { mbar_arrive_cta(BAR(kfree), 0); mbar_arrive_cta(BAR(kfree), 1); }
        if (warp >= 8) {
            const int t2 = tid - 256;
            float csum[10];
            if (K_CLR == 0 && warp == 11 && elect_one()) clear_fin(sb + Q_ZERO);
            __syncwarp();
            if (t2 < 64) g_sums[0][0][64 * bx + t2] = 0.f;
#pragma unroll
            for (int i = 0; i < 3; i++)
                if (t2 + 128 * i < 320) stg128(&g_halo[bx][0][0][0] + t2 + 128 * i, make_uint4(0, 0, 0, 0));
            if (warp == 8) asm volatile("bar.arrive 13, 128;" ::: "memory"); else named_bar(13, 128);
            if (warp > 8) {
                const int hw = warp - 9, mi = lane >> 3, mj = lane & 7;
                mbar_wait(BAR(idx), 0);
                if (hw == 2 && elect_one()) { bulk_s2g(&g_wop[hg][5 * blk], sb + Q_WOT, 6400); bulk_commit(); }
                __syncwarp();
                mbar_wait(BAR(full), 0);
                mbar_wait(BAR(full) + 8, 0);
#pragma unroll
                for (int f = 0; f < 10; f++) csum[f] = 0.f;
#pragma unroll K_CSU
                for (int G = 0; G < 5; G++) {
                    const int row = c0 + 40 * rank + 8 * G + mj;
                    const uint32_t b = sb + (row >> 6) * Q_SB + Q_AB + ((row >> 5) & 1) * 15360;
                    uint32_t r[10];
                    ldsm_x4_t(r[0], r[1], r[2], r[3], b + hw * 4096 + (row & 31) * 128 + ((mi ^ mj) << 4));
                    ldsm_x4_t(r[4], r[5], r[6], r[7], b + hw * 4096 + (row & 31) * 128 + (((4 + mi) ^ mj) << 4));
                    ldsm_x2_t(r[8], r[9], b + 12288 + hw * 1024 + (row & 31) * 32 + (((mi & 1) ^ (mj >> 2)) << 4));
#pragma unroll
                    for (int f = 0; f < 10; f++) csum[f] += bf_lo(r[f]) + bf_hi(r[f]);
                }
                const int q = lane & 3;
                float t[3];
#pragma unroll
                for (int j = 0; j < 3; j++) {
                    float v[4];
#pragma unroll
                    for (int k = 0; k < 4; k++) v[k] = 4 * j + k < 10 ? csum[4 * j + k] : 0.f;
                    const float a0 = ((q & 2) ? v[2] : v[0]) + __shfl_xor_sync(~0u, (q & 2) ? v[0] : v[2], 2);
                    const float a1 = ((q & 2) ? v[3] : v[1]) + __shfl_xor_sync(~0u, (q & 2) ? v[1] : v[3], 2);
                    t[j] = ((q & 1) ? a1 : a0) + __shfl_xor_sync(~0u, (q & 1) ? a0 : a1, 1);
                }
                st_ll4(&g_csp[hg][blk][tid - 288], ~EPOCH & 1u, __float_as_uint(t[0]), __float_as_uint(t[1]), __float_as_uint(t[2]));
            }
        }
        TS(1);
    }

    uint4 fa1[4], ftw[4];
    auto conv_tables = [&] {
#pragma unroll
        for (int i = 0; i < 4; i++) { fa1[i] = ldg_tab(i, tid & 127); ftw[i] = ldg_tab(8 + i, tid & 127); }
    };
    auto conv_done = [&] {
        if (layer == 0) {
            named_bar(1 + (warp >> 2), 128);
            if ((tid & 127) == 0) {
                mbar_arrive(BAR(fdone));
                if (K_CLR == 9 && tid == 256) { bulk_wait(); fence_async_global(); }
                grid_arrive(g_bar[2][hg]);
            }
            __syncwarp();
        }
        TS(20);
    };
    if (warp >= 8) {
    asm volatile("setmaxnreg.dec.sync.aligned.u32 %0;" ::"n"(504 - 2 * R_CONS));
#pragma unroll 1
    for (; layer < 2; layer++, bars += sizeof(Bars)) {
        indices();
        TS_PHASE(2 * layer);
        if (warp == 8) {
            if (layer) {
                grid_wait(g_bar[2][0], 8, 48 * (EPOCH + 1), lane);
                mbar_wait(BAR(fdone) - sizeof(Bars), 0);
                fence_async_global();
                TS(1);
            }
            if (elect_one()) {
#pragma unroll 1
                for (int it = layer ? 0 : 2; it < 10; it++) {
                    if (it >= Q_ST) mbar_wait(BAR(empty) + 8 * (it & (Q_ST - 1)), ((it >> 2) - 1) & 1);
                    else if (layer == 0) mbar_wait(BAR(kfree), 0);
                    else if (it > 0 && Q_WAITFOR(it) >= 0) mbar_wait(BAR(full) + 8 * Q_WAITFOR(it), 0);
                    if (it == Q_ST) mbar_wait(BAR(hdone), 0);
                    issue_x(it);
                    if (layer == 0 || it >= F_PRE) issue_w(BAR(full), it, rank);
                }
                if (T_PF) { prefetch_tmap(TMAP(5) + layer); prefetch_tmap(TMAP(7)); }
                if (layer == 0) { mbar_wait(BAR(prep), 0); fence_async_global(); }
#pragma unroll 1
                for (int j = 0; j < 8; j++) {
                    const int b = (j + 1) >> 2;
                    const uint32_t fb = BAR(wfull) + 8 * b;
                    if (j == 0 || j == 3 || j == 7) {
                        mbar_wait(BAR(empty) + 8 * ((2 + b) & 3), b < 2);
                        TS(11 + b);
                        mbar_expect(fb, (b == 0 ? 3 : b == 1 ? 4 : 1) * 12800);
                    }
                    bulk_g2s_mc(sb + w_grp(j) + rank * 6400, &g_wop[hg][osrc_of(j) * 10 + rank * 5], 6400, fb, 3);
                }
                mbar_expect(BAR(res), 20480);
                if (layer == 0) tma3d(sb + W_RES, TMAP(1), hg * 80, blk * 64, 0, BAR(res));
                tma3d(sb + W_RES + (layer ? 0 : 16384), TMAP(5) + layer, layer ? blk * 64 : hg * 80 + 64, layer ? hg * 80 : blk * 64, 0, BAR(res));
                if (layer == 0) { mbar_wait(BAR(kdone), 0); fence_async_global(); }
                mbar_expect(BAR(kf2), (2 - layer) * 8192);
                bulk_g2s(sb + F_EO + 2 * 8192, g_keo[bx][2], 8192, BAR(kf2));
                if (layer == 0) bulk_g2s(sb + F_S23, c_fft + 18 * 512, 8192, BAR(kf2));
            }
            __syncwarp();
        } else {
            const int ht = tid - 288, hw = warp - 9, mi = lane >> 3, mj = lane & 7, g = lane >> 2, q = lane & 3;
            auto F = [](uint32_t x) { return __uint_as_float(x); };
            auto U = [](float x) { return __float_as_uint(x); };
            const uint32_t lb = layer ^ 1, eb = ~EPOCH & 1u;
            mbar_wait(BAR(full), 0);
            mbar_wait(BAR(full) + 8, 0);
            if (ht == 0) TSX(2, 2);
            uint32_t xf[3][20];
#pragma unroll
            for (int i = 0; i < 3; i++) {
                const int tile = min(hw + 3 * i, 7);
#pragma unroll
                for (int k = 0; k < 5; k++) {
                    const int ch = c0 + 16 * k + 8 * (mi >> 1), tok = 16 * (tile & 3) + 8 * (mi & 1);
                    const uint32_t a = sb + (ch >> 6) * Q_SB + (tile >> 2) * 8192;
                    if (layer == 0) ldsm_x4(xf[i][4 * k], xf[i][4 * k + 1], xf[i][4 * k + 2], xf[i][4 * k + 3], a + (tok + mj) * 128 + ((((ch & 63) >> 3) ^ mj) << 4));
                    else ldsm_x4_t(xf[i][4 * k], xf[i][4 * k + 1], xf[i][4 * k + 2], xf[i][4 * k + 3], a + ((ch & 63) + mj) * 128 + (((tok >> 3) ^ mj) << 4));
                }
            }
            fence_async_smem();
            __syncwarp();
            if (lane == 0) { mbar_arrive_cta(BAR(hdone), 0); mbar_arrive_cta(BAR(hdone), 1); }
            if (ht == 0) TSX(2, 3);
            if (layer == 0) {
                if (hw == 2 && elect_one()) { bulk_wait(); fence_async_global(); grid_arrive(g_bar[3][hg]); }
                __syncwarp();
                mbar_wait(BAR(kfree), 0);
            }
            if (ht == 0) TSX(2, 8);
#pragma unroll 1
            for (int tile = hw; tile < 8; tile += 3) {
                float a[4] = {0.f, 0.f, 0.f, 0.f};
#pragma unroll
                for (int j = 0; j < 20; j++) {
                    const float lo = bf_lo(xf[0][j]), hi = bf_hi(xf[0][j]);
                    a[2 * (j & 1)] += lo + hi; a[2 * (j & 1) + 1] = fmaf(lo, lo, fmaf(hi, hi, a[2 * (j & 1) + 1]));
                    xf[0][j] = xf[1][j]; xf[1][j] = xf[2][j];
                }
#pragma unroll
                for (int j = 0; j < 4; j++) { a[j] += __shfl_xor_sync(~0u, a[j], 1); a[j] += __shfl_xor_sync(~0u, a[j], 2); }
                if (q == 0) st_ll4(&g_stp[blk][hg][8 * tile + g], (U(a[0]) & ~1u) | lb, U(a[1]), U(a[2]), U(a[3]));
            }
            if (ht == 0) TSX(2, 4);
            if (layer == 0) {
                float t[4] = {0.f, 0.f, 0.f, 0.f};
                uint4 v[16];
                int spin = 0;
                uint32_t bad;
                do {
                    bad = 0;
#pragma unroll
                    for (int j = 0; j < 16; j++) v[j] = ld_ll4(&g_csp[hg][j][ht]);
#pragma unroll
                    for (int j = 0; j < 16; j++) bad |= v[j].x ^ eb;
                } while ((bad & 1u) && ++spin < (1 << 18));
#pragma unroll
                for (int j = 0; j < 16; j++) { t[0] += F(v[j].y); t[1] += F(v[j].z); t[2] += F(v[j].w); }
#pragma unroll
                for (int j = 0; j < 3; j++) if (q + 4 * j < 10) s_cs[80 * hw + 20 * (g >> 1) + 2 * (q + 4 * j) + (g & 1)] = t[j];
                if (hw == 2) grid_wait(g_bar[3][0], 8, 16 * (EPOCH + 1), lane);
            }
            if (ht == 0) TSX(2, 15);
            if (ht < 80) {
                const bool halo = ht >= 64;
                const int p = halo ? (ht >> 3) & 1 : ht >> 5, i = halo ? (ht & 7) - 8 : 8 + 2 * (ht & 24) + (ht & 7);
                const uint4* src = &g_stp[halo && blk ? blk - 1 : blk][0][halo ? 32 * p + 24 + (ht & 7) : ht];
                uint4 v[8];
                int spin = 0;
                uint32_t bad;
                do {
                    bad = 0;
#pragma unroll
                    for (int j = 0; j < 8; j++) v[j] = ld_ll4(src + 64 * j);
#pragma unroll
                    for (int j = 0; j < 8; j++) bad |= v[j].x ^ lb;
                } while ((bad & 1u) && ++spin < (1 << 18));
                float t[4] = {0.f, 0.f, 0.f, 0.f};
#pragma unroll
                for (int j = 0; j < 8; j++) { t[0] += F(v[j].x); t[1] += F(v[j].y); t[2] += F(v[j].z); t[3] += F(v[j].w); }
                const uint32_t s0 = ln_finish_packed(t[0], t[1]), s1 = ln_finish_packed(t[2], t[3]);
                if (!halo) { s_mean[p][i - 8] = bf_hi(s0); s_mean[p][i] = bf_hi(s1); s_rstd[p][i] = frcp(bf_lo(s0)); }
                s_rstd[p][i + 8] = frcp(bf_lo(s1));
            }
            fence_acquire();
            mbar_arrive(BAR(prep));
            if (ht == 0) TSX(2, 5);
            if (layer == 0) {
                __syncwarp();
                kgen_expand(bx, sb + Q_KDUMP, &s_kg, ht TS_PASS);
                if (K_CLR == 9) {
                    named_bar(4, 96);
#pragma unroll
                    for (int i = 0; i < 3; i++) if (ht + 96 * i < 256) sts128(sb + F_S23 + 8192 + (ht + 96 * i) * 16, make_uint4(0, 0, 0, 0));
                }
                fence_async_smem();
                named_bar(4, 96);
                if (ht == 0) { fence_release(); mbar_arrive(BAR(kdone)); }
                if (ht == 0) TSX(2, 7);
            }
        }
        __syncwarp();
        TS_PHASE(2 * layer + 1);
        TS(0);
        indices();
        conv_tables();
        conv_wg<1>(5 * bx + 4, layer, sb + F_EO + 2 * 8192, sb + 2 * Q_SB, sb + F_S23, BAR(kf2), s2u(&s_kg.kexp[4]), sb + 3 * Q_SB, BAR(st), warp, lane, fa1, ftw,
        [] {}, [&] {
            if (warp == 8) {
                mbar_wait(BAR(att), 0);
                if (elect_one()) {
                    fence_async_smem();
                    mbar_expect(BAR(kf), 2 * 8192);
                    bulk_g2s(sb + F_EO, g_keo[bx][0], 2 * 8192, BAR(kf));
                }
                __syncwarp();
                grid_wait(g_bar[layer][0], 8, 32 * (EPOCH + 1), lane);
                if (!F_SHARE && lane < 4) mbar_arrive(BAR(ardy));
            }
            if (F_SHARE) named_bar(3, 128); else mbar_wait(BAR(ardy), 0);
        }, [&] {
            if (K_CLR == 9 && layer == 0 && tid == 256) clear_fin(sb + F_S23 + 8192);
            __syncwarp();
            if (F_SHARE && lane == 0) mbar_arrive(BAR(ardy));
        }, [&] {
            if (T_PF && tid == 352) prefetch_tmap(layer ? TMAP(9) : TMAP(2));
            if (layer == 0 && warp - 8 < F_PRE && elect_one()) issue_w(BAR(full) + sizeof(Bars), warp - 8, rank);
            __syncwarp();
        } TS_PASS);
        conv_done();
    }
    } else {
#pragma unroll 1
    for (; layer < 2; layer++, bars += sizeof(Bars)) {
    indices();
    TS_PHASE(2 * layer);
    const int wg = warp >> 2, w = warp & 3;
    const int mi = lane >> 3, mj = lane & 7, g = lane >> 2, q = lane & 3;
    TS(2);
    float acc[120];
#pragma unroll
    for (int i = 0; i < 120; i++) acc[i] = 0.f;
    auto release = [&](int it) {
        if (lane == 0) { mbar_arrive_cta(BAR(empty) + 8 * (it & (Q_ST - 1)), 0); mbar_arrive_cta(BAR(empty) + 8 * (it & (Q_ST - 1)), 1); }
    };
#pragma unroll 1
    for (int it = 0; it < 10; it++) {
        const int s = it & (Q_ST - 1);
        const uint32_t st = sb + s * Q_SB;
        const bool hold = wg == 1 && it == Q_S0;
        if (hold) {
            wg_wait<0>();
            release(it - 1);
            mbar_wait(BAR(go), 0);
        }
        mbar_wait(BAR(full) + 8 * (s), (it >> 2) & 1);
        if (it < 2) TS(3 + it);
        if (it == 6) TS(5);
        if (it == 9) TS(6);
        const uint64_t da = mkdesc(st + wg * 8192, 16, 1024, 1);
        const uint64_t db = mkdesc(st + Q_AB, 4096, 1024, 1);
        const uint64_t dr = mkdesc(st + Q_AB + 12288, 1024, 256, 3);
        if (layer == 0) {
            wg_fence();
#pragma unroll
            for (int ks = 0; ks < 4; ks++) {
                const int sc = 1;
                wgmma_n192<0, 1>(*(float(*)[96]) & acc[0], da + ks * 2, db + (ks >> 1) * 960 + (ks & 1) * 128, sc);
                wgmma_n48<0, 1>(*(float(*)[24]) & acc[96], da + ks * 2, dr + (ks >> 1) * 960 + (ks & 1) * 32, sc);
            }
            wg_commit();
        } else {
            wg_fence();
#pragma unroll
            for (int ks = 0; ks < 4; ks++) {
                const int sc = 1;
                wgmma_n192<1, 1>(*(float(*)[96]) & acc[0], da + ks * 128, db + (ks >> 1) * 960 + (ks & 1) * 128, sc);
                wgmma_n48<1, 1>(*(float(*)[24]) & acc[96], da + ks * 128, dr + (ks >> 1) * 960 + (ks & 1) * 32, sc);
            }
            wg_commit();
        }
        wg_wait<1>();
        if (it > 0 && !hold) release(it - 1);
    }
    if (wg == 0 && lane == 0) mbar_arrive(BAR(go));
    asm volatile("setmaxnreg.inc.sync.aligned.u32 %0;" ::"n"(R_CONS));
    mbar_wait(BAR(prep), 0);
    const uint32_t ob = layer ^ 1;
    const bool first = (blk == 0 && w == 0);
    const bool sel0 = (2 * q > g), sel1 = (2 * q + 1 > g);
    constexpr float SC = 0.22360679774997896f * 1.4426950408889634f;
    const float m0 = s_mean[wg][16 * w + g], m1 = s_mean[wg][8 + 16 * w + g];
    uint4 cs[3][5];
    auto cs_load = [&](int p) {
#pragma unroll
        for (int i = 0; i < 5; i++) cs[p][i] = lds128(s2u(&s_cs[80 * p + 20 * q + 4 * i]));
    };
    if (A_CSPRE >= 1) cs_load(1);
    if (A_CSPRE >= 2) cs_load(2);
    wg_wait<0>();
    if (A_CSPRE < 1) cs_load(1);
    if (A_CSPRE < 2) cs_load(2);
    TS(7);
    if (lane == 0) mbar_arrive(BAR(qdone));
    uint32_t ql[10], qh[10], kl[10], kh[10], vl[10], vh[10];
    auto fold = [&](int p, int f, int h) {
        const int j = (f < 8) ? 8 * p + f : 24 + 2 * p + (f - 8);
        const float c0 = __uint_as_float(u4(cs[p][f >> 1], 2 * (f & 1))), c1 = __uint_as_float(u4(cs[p][f >> 1], 2 * (f & 1) + 1));
        const float m = h ? m1 : m0;
        return pack2(fmaf(-m, c0, acc[4 * j + 2 * h]), fmaf(-m, c1, acc[4 * j + 2 * h + 1]));
    };
#pragma unroll
    for (int f = 0; f < 10; f++) { kh[f] = fold(1, f, 1); vh[f] = fold(2, f, 1); }
    if (w == 3) {
        uint4* hp = &g_halo[bx][wg][0][lane];
        st_ll4(hp, (kh[0] & ~1u) | ob, kh[1], kh[3], kh[4]); st_ll4(hp + 32, (kh[5] & ~1u) | ob, kh[6], kh[8], kh[9]);
        st_ll4(hp + 64, (vh[0] & ~1u) | ob, vh[1], vh[2], vh[3]); st_ll4(hp + 96, (vh[4] & ~1u) | ob, vh[5], vh[6], vh[7]);
        st_ll4(hp + 128, (vh[8] & ~1u) | ob, vh[9], kh[2], kh[7]);
    } else {
        const uint32_t a = sb + Q_EOFF + (warp - wg) * Q_ESLOT + mj * Q_EROW + mi * 16;
        stsm_x4(a, kh[0], kh[1], kh[3], kh[4]);
        stsm_x4(a + 64, kh[5], kh[6], kh[8], kh[9]);
        stsm_x4(a + 128, vh[0], vh[1], vh[2], vh[3]);
        stsm_x4(a + 192, vh[4], vh[5], vh[6], vh[7]);
        stsm_x4(a + 256, vh[8], vh[9], kh[2], kh[7]);
        __syncwarp();
        if (lane == 0) mbar_arrive(BAR(ex) + 8 * warp);
    }
    TS(9);
    cs_load(0);
#pragma unroll
    for (int f = 0; f < 10; f++) { kl[f] = fold(1, f, 0); vl[f] = fold(2, f, 0); }
#pragma unroll
    for (int f = 0; f < 10; f++) { ql[f] = fold(0, f, 0); qh[f] = fold(0, f, 1); }
    auto rs = [&](int i) { return __uint_as_float(lds32(s2u(&s_rstd[wg][16 * w + i]))); };
    const float kx0 = rs(2 * q + (sel0 ? 0 : 8)), kx1 = rs(2 * q + (sel1 ? 1 : 9)), ky0 = rs(2 * q + (sel0 ? 8 : 16)), ky1 = rs(2 * q + (sel1 ? 9 : 17));
    const float rx = SC * rs(8 + g), ry = SC * rs(16 + g), cx0 = rx * kx0, cx1 = rx * kx1, cy0 = ry * ky0, cy1 = ry * ky1;
    uint4 hv[5];
    const uint4* hp = &g_halo[bx - 1][wg][0][lane];
    auto prev = [&] {
        if (w > 0) {
            const uint32_t a = sb + Q_EOFF + (warp - wg - 1) * Q_ESLOT + mj * Q_EROW + mi * 16;
            mbar_wait(BAR(ex) + 8 * (warp - 1), 0);
            ldsm_x4(hv[0].x, hv[0].y, hv[0].z, hv[0].w, a);
            ldsm_x4(hv[1].x, hv[1].y, hv[1].z, hv[1].w, a + 64);
            ldsm_x4_t(hv[2].x, hv[2].y, hv[2].z, hv[2].w, a + 128);
            ldsm_x4_t(hv[3].x, hv[3].y, hv[3].z, hv[3].w, a + 192);
            ldsm_x2_t(hv[4].x, hv[4].y, a + 256);
            ldsm_x2(hv[4].z, hv[4].w, a + 288 - (lane >> 4) * 32);
        } else if (blk > 0) {
#pragma unroll
            for (int f = 0; f < 5; f++) hv[f] = ld_ll4(hp + 32 * f);
        } else {
#pragma unroll
            for (int f = 0; f < 5; f++) hv[f] = make_uint4(0, 0, 0, 0);
        }
    };
    if (A_HPOS == 0) prev();
    uint32_t vt[10][2];
#pragma unroll
    for (int f = 0; f < 10; f++) { vt[f][0] = movm_t(vl[f]); vt[f][1] = movm_t(vh[f]); }
    if (A_HPOS == 1) prev();
    TS(10);
    auto FA = [](int h) { return h == 0 ? 0 : h == 1 ? 3 : h == 2 ? 5 : 8; };
    auto FH = [](int h) { return h < 2 ? 2 : 7; };
    const uint32_t pm = (sel0 ? 0xFFFFu : 0u) | (sel1 ? 0xFFFF0000u : 0u);
    auto softmax = [&](float x0, float x1, float k0, float k1) {
        float mx = fmaxf(x0, x1);
        mx = fmaxf(mx, __shfl_xor_sync(~0u, mx, 1));
        mx = fmaxf(mx, __shfl_xor_sync(~0u, mx, 2));
        x0 = ex2(x0 - mx); x1 = ex2(x1 - mx);
        float sx = x0 + x1;
        sx += __shfl_xor_sync(~0u, sx, 1);
        sx += __shfl_xor_sync(~0u, sx, 2);
        const float ix = frcp(sx);
        return pack2(x0 * k0 * ix, x1 * k1 * ix);
    };
    uint32_t qm[4][2], py[4];
    float sl[4][2];
#pragma unroll
    for (int h = 0; h < 4; h++) {
        const int fa = FA(h), fb = fa + 1, fh = FH(h);
        const bool mine = (h & 1) ? (q >= 2) : (q < 2);
        qm[h][0] = mine ? ql[fh] : 0u; qm[h][1] = mine ? qh[fh] : 0u;
        float S1[4] = {0.f, 0.f, 0.f, 0.f}, S2[4] = {0.f, 0.f, 0.f, 0.f};
        mma16816(S1, ql[fa], qh[fa], ql[fb], qh[fb], kl[fa], kl[fb]); mma1688(S1, qm[h][0], qm[h][1], kl[fh]);
        mma16816(S2, ql[fa], qh[fa], ql[fb], qh[fb], kh[fa], kh[fb]); mma1688(S2, qm[h][0], qm[h][1], kh[fh]);
        sl[h][0] = S1[0]; sl[h][1] = S1[1];
        py[h] = softmax((sel0 ? S1[2] : S2[2]) * cy0, (sel1 ? S1[3] : S2[3]) * cy1, ky0, ky1);
    }
    TS(11);
    if (w == 0 && blk > 0) {
        int spin = 0;
        while (__any_sync(~0u, ((hv[0].x ^ ob) | (hv[1].x ^ ob) | (hv[2].x ^ ob) | (hv[3].x ^ ob) | (hv[4].x ^ ob)) & 1u) && ++spin < (1 << 18)) {
#pragma unroll
            for (int f = 0; f < 5; f++) hv[f] = ld_ll4(hp + 32 * f);
        }
#pragma unroll
        for (int f = 2; f < 4; f++) hv[f] = make_uint4(movm_t(hv[f].x), movm_t(hv[f].y), movm_t(hv[f].z), movm_t(hv[f].w));
        hv[4].x = movm_t(hv[4].x); hv[4].y = movm_t(hv[4].y);
    }
    const uint32_t kp[10] = {hv[0].x, hv[0].y, hv[4].z, hv[0].z, hv[0].w, hv[1].x, hv[1].y, hv[4].w, hv[1].z, hv[1].w};
    const uint32_t vp[10] = {hv[2].x, hv[2].y, hv[2].z, hv[2].w, hv[3].x, hv[3].y, hv[3].z, hv[3].w, hv[4].x, hv[4].y};
    TS(12);
    const float bx0 = first && sel0 ? -INFINITY : 0.f, bx1 = first && sel1 ? -INFINITY : 0.f;
    float oacc[10][4];
#pragma unroll
    for (int h = 0; h < 4; h++) {
        const int fa = FA(h), fb = fa + 1, fh = FH(h);
        const bool mine = (h & 1) ? (q >= 2) : (q < 2);
        float S0[4] = {0.f, 0.f, 0.f, 0.f};
        mma16816(S0, ql[fa], qh[fa], ql[fb], qh[fb], kp[fa], kp[fb]); mma1688(S0, qm[h][0], qm[h][1], kp[fh]);
        const uint32_t px = softmax(fmaf(sel0 ? S0[0] : sl[h][0], cx0, bx0), fmaf(sel1 ? S0[1] : sl[h][1], cx1, bx1), kx0, kx1);
#pragma unroll
        for (int i = 0; i < 3; i++) {
            const int f = (i == 0) ? fa : (i == 1) ? fb : fh;
            float O[4] = {0.f, 0.f, 0.f, 0.f};
            mma16816(O, px & ~pm, py[h] & pm, 0u, py[h] & ~pm, vt[f][0], vt[f][1]);
            mma1688(O, px & pm, 0u, vp[f]);
            if (i < 2 || !(h & 1) || mine) { oacc[f][0] = O[0]; oacc[f][1] = O[1]; oacc[f][2] = O[2]; oacc[f][3] = O[3]; }
        }
    }
    TS(13);
    constexpr int ON = O_RING ? O_DEPTH + 2 : 7;
    uint4 of[ON][5];
    {
        uint4* dst = &g_of[hg][blk][warp][0][lane];
#pragma unroll
        for (int k = 0; k < 5; k++) {
            of[0][k] = make_uint4((pack2(oacc[2 * k][0], oacc[2 * k][1]) & ~1u) | ob, pack2(oacc[2 * k][2], oacc[2 * k][3]),
                                  pack2(oacc[2 * k + 1][0], oacc[2 * k + 1][1]), pack2(oacc[2 * k + 1][2], oacc[2 * k + 1][3]));
            st_ll4(dst + 32 * k, of[0][k].x, of[0][k].y, of[0][k].z, of[0][k].w);
        }
    }
    if (Q_WGATE && wg == 1 && lane == 0) mbar_arrive(BAR(att1));
    TS(14);
    const uint4* osrc = &g_of[0][blk][warp][0][lane];
    auto oload = [&](int j) {
        const uint4* p = osrc + osrc_of(j) * 20480;
#pragma unroll
        for (int k = 0; k < 5; k++) of[j % ON][k] = ld_ll4(p + 32 * k);
    };
    float aw[40];
    auto omma = [&](int j) {
        const uint64_t dm = mkdesc(sb + w_grp(j), 1280, 128, 0);
        wg_fence();
#pragma unroll
        for (int k = 0; k < 5; k++) wgmma_rs80(aw, of[j % ON][k], dm + k * 160, j + k > 0);
        wg_commit();
    };
    if (Q_WGATE && wg == 0) mbar_wait(BAR(att1), 0);
    mbar_wait(BAR(wfull), 0);
    omma(0);
    TS(8);
    {
        const uint32_t* pp = &g_of[osrc_of(1 + min(lane, 6))][blk][warp][4][31].x;
        uint32_t v, m;
        int spin = 0;
        do {
            asm volatile("ld.relaxed.gpu.global.u32 %0, [%1];" : "=r"(v) : "l"(pp) : "memory");
            m = __ballot_sync(~0u, (v & 1u) != ob);
        } while ((m & O_MASK) && ++spin < (1 << 18));
        TS(15);
        if (O_GATE) named_bar(O_GATE == 1 ? 1 + wg : 9, O_GATE == 1 ? 128 : 256);
#pragma unroll
        for (int j = 1; j <= O_DEPTH; j++) oload(j);
        TS(16);
    }
#pragma unroll
    for (int j = 1; j < 8; j++) {
        if (j == 3 || j == 7) mbar_wait(BAR(wfull) + 8 * ((j + 1) >> 2), 0);
        int spin = 0;
        while (true) {
            const uint4* f = of[j % ON];
            const uint32_t bad = ((f[0].x ^ ob) | (f[1].x ^ ob) | (f[2].x ^ ob) | (f[3].x ^ ob) | (f[4].x ^ ob)) & 1u;
            if (__all_sync(~0u, !bad) || ++spin >= (1 << 18)) break;
            oload(j);
        }
        if (j + O_DEPTH < 8) { if (O_RING || j == 2) wg_wait<1>(); oload(j + O_DEPTH); }
        if (j == 1) TS(17);
        if (j == 5) TS(18);
        omma(j);
        if (j == O_KAT && lane == 0) mbar_arrive(BAR(att));
    }
    wg_wait<2>();
    uint32_t res[20];
    mbar_wait(BAR(res), 0);
    const uint32_t ta = (8 * (mi >> 1) + mj) * 128 + (((2 * w + (mi & 1)) ^ mj) << 4);
    if (layer == 0) {
        const int tok = 16 * w + 8 * (mi & 1) + mj;
#pragma unroll
        for (int k = 0; k < 4; k++)
            ldsm_x4(res[4 * k], res[4 * k + 1], res[4 * k + 2], res[4 * k + 3], sb + W_RES + wg * 8192 + tok * 128 + (((2 * k + (mi >> 1)) ^ mj) << 4));
        ldsm_x4(res[16], res[17], res[18], res[19], sb + W_RES + 16384 + wg * 2048 + tok * 32 + (((mi >> 1) ^ (mj >> 2)) << 4));
    } else {
#pragma unroll
        for (int k = 0; k < 5; k++) ldsm_x4_t(res[4 * k], res[4 * k + 1], res[4 * k + 2], res[4 * k + 3], sb + W_RES + wg * 10240 + k * 2048 + ta);
    }
    mbar_wait(BAR(qdone), 0);
    wg_wait<0>();
    TS(19);
#pragma unroll
    for (int i = 0; i < 20; i++) {
        const uint32_t y = pack2(aw[2 * i], aw[2 * i + 1]);
        asm("add.rn.bf16x2 %0, %0, %1;" : "+r"(res[i]) : "r"(y));
    }
#pragma unroll
    for (int k = 0; k < 5; k++) stsm_x4_t(sb + W_OUT + wg * 10240 + k * 2048 + ta, res[4 * k], res[4 * k + 1], res[4 * k + 2], res[4 * k + 3]);
    fence_async_smem();
    named_bar(1 + wg, 128);
    if (w == 0 && elect_one()) {
        asm volatile("cp.async.bulk.tensor.2d.global.shared::cta.bulk_group [%0, {%2, %3}], [%1];"
                     ::"l"(TMAP(7)), "r"(sb + W_OUT + wg * 10240), "r"(1024 * wg + 64 * blk), "r"(hg * 80) : "memory");
        bulk_commit();
    }
    __syncwarp();
    conv_tables();
    TS(20);
    {
        float sm[4] = {0.f, 0.f, 0.f, 0.f}, d0[4] = {0.f, 0.f, 0.f, 0.f}, d1[4] = {0.f, 0.f, 0.f, 0.f};
#pragma unroll
        for (int k = 0; k < 5; k++) {
            mma16816(sm, res[4 * k], res[4 * k + 1], res[4 * k + 2], res[4 * k + 3], 0x3F803F80u, 0x3F803F80u);
            mma16816(d0, res[4 * k], res[4 * k + 1], res[4 * k + 2], res[4 * k + 3], res[4 * k], res[4 * k + 2]);
            mma16816(d1, res[4 * k], res[4 * k + 1], res[4 * k + 2], res[4 * k + 3], res[4 * k + 1], res[4 * k + 3]);
        }
        const bool diag = q == (g >> 1);
        if (diag || q == ((g >> 1) ^ 1)) {
            float* dst = g_sums[layer][diag] + 1024 * wg + 64 * blk + 16 * w + g;
            asm volatile("red.global.add.f32 [%0], %1;" ::"l"(dst), "f"(diag ? ((g & 1) ? d0[1] : d0[0]) : sm[0]) : "memory");
            asm volatile("red.global.add.f32 [%0], %1;" ::"l"(dst + 8), "f"(diag ? ((g & 1) ? d1[3] : d1[2]) : sm[2]) : "memory");
        }
    }
    TS(21);
    named_bar(1 + wg, 128);
    TS(22);
    TS_PHASE(2 * layer + 1);
    TS(0);
    indices();
    mbar_wait(BAR(kf2), 0);
    conv_wg<2>(5 * bx + 2 * (warp >> 2), layer, sb + F_EO + (warp >> 2) * 8192, sb + (warp >> 2) * Q_SB, sb + F_S23, BAR(kf), s2u(&s_kg.kexp[2 * (warp >> 2)]),
               sb + 3 * Q_SB, BAR(st), warp, lane, fa1, ftw, [&] {
        if ((warp & 3) == 0 && elect_one()) { bulk_wait(); fence_async_global(); grid_arrive(g_bar[layer][hg]); }
        __syncwarp();
    }, [&] { mbar_wait(BAR(ardy), 0); }, [] {}, [] {} TS_PASS);
    conv_done();
    asm volatile("setmaxnreg.dec.sync.aligned.u32 168;");
    }
    named_bar(1 + (warp >> 2), 128);
    asm volatile("setmaxnreg.dec.sync.aligned.u32 %0;" ::"n"(504 - 2 * R_CONS));
    }
    indices();
    __syncthreads();
    if (FIN_DELAY) { const long long t0 = clock64(); while (clock64() - t0 < FIN_DELAY) {} }
    if (tid < 320) {
        const int p = warp & 1, cq = 4 * (warp >> 1) + (lane >> 3), tg = lane & 7;
        const uint4* src = (const uint4*)(g_x2T[1] + (size_t)(80 * hg + 4 * cq) * XP + 1024 * p + 64 * blk + 8 * tg);
        uint4 v[4];
#pragma unroll
        for (int i = 0; i < 4; i++) v[i] = make_uint4(0, 0, 0, 0);
        int spin = 0;
        while (true) {
            bool ok = true;
#pragma unroll
            for (int i = 0; i < 4; i++) if (v[i].x == 0u || v[i].z == 0u) v[i] = ld_ll4(src + i * (XP / 8));
#pragma unroll
            for (int i = 0; i < 4; i++) ok = ok && v[i].x != 0u && v[i].z != 0u;
            if (ok || ++spin >= (1 << 18)) break;
            if (FIN_SLEEP) __nanosleep(FIN_SLEEP);
        }
        TS(21);
#pragma unroll
        for (int i = 0; i < 8; i++) {
            const uint32_t sel = (i & 1) ? 0x7632 : 0x5410;
            asm volatile("st.shared.v2.u32 [%0], {%1, %2};" ::"r"(sb + (8 * (2 * i + p) + tg) * 160 + cq * 8),
                         "r"(__byte_perm(u4(v[0], i >> 1), u4(v[1], i >> 1), sel)), "r"(__byte_perm(u4(v[2], i >> 1), u4(v[3], i >> 1), sel)) : "memory");
        }
        fence_async_smem();
    }
    __syncthreads();
    if (warp == 0 && elect_one()) {
        asm volatile("cp.async.bulk.tensor.3d.global.shared::cta.bulk_group [%0, {%2, %3, 0}], [%1];" ::"l"(TMAP(9)), "r"(sb), "r"(80 * hg), "r"(8 * blk) : "memory");
        bulk_commit();
        asm volatile("cp.async.bulk.wait_group.read 0;" ::: "memory");
    }
    if (bx == 0 && tid == 0) g_epoch = EPOCH + 1;
    TS(22);
    TS_END;
}
typedef CUresult (*EncodeTiledFn)(CUtensorMap*, CUtensorMapDataType, cuuint32_t, void*, const cuuint64_t*, const cuuint64_t*, const cuuint32_t*,
                                  const cuuint32_t*, CUtensorMapInterleave, CUtensorMapSwizzle, CUtensorMapL2promotion, CUtensorMapFloatOOBfill);

static void make_map(EncodeTiledFn enc, CUtensorMap* m, const void* base, int rank, const cuuint64_t* dims, const cuuint64_t* strides,
                     const cuuint32_t* box, CUtensorMapSwizzle sw) {
    cuuint32_t es[4] = {1, 1, 1, 1};
    enc(m, CU_TENSOR_MAP_DATA_TYPE_BFLOAT16, rank, (void*)base, dims, strides, box, es, CU_TENSOR_MAP_INTERLEAVE_NONE, sw,
        sw == CU_TENSOR_MAP_SWIZZLE_128B ? CU_TENSOR_MAP_L2_PROMOTION_L2_128B : CU_TENSOR_MAP_L2_PROMOTION_NONE, CU_TENSOR_MAP_FLOAT_OOB_FILL_NONE);
}

template <typename... KArgs, typename... Args>
static void launch(void (*kern)(KArgs...), int grid, int block, int smem, int cluster, bool pdl, Args... args) {
    cudaLaunchConfig_t cfg = {};
    cfg.gridDim = dim3(grid); cfg.blockDim = dim3(block); cfg.dynamicSmemBytes = smem; cfg.stream = cudaStreamPerThread;
    cudaLaunchAttribute at[2];
    int n = 0;
    if (cluster > 1) { at[n].id = cudaLaunchAttributeClusterDimension; at[n].val.clusterDim.x = cluster; at[n].val.clusterDim.y = 1; at[n].val.clusterDim.z = 1; n++; }
    if (pdl) { at[n].id = cudaLaunchAttributeProgrammaticStreamSerialization; at[n].val.programmaticStreamSerializationAllowed = 1; n++; }
    cfg.attrs = at; cfg.numAttrs = n;
    cudaLaunchKernelEx(&cfg, kern, KArgs(args)...);
}

struct HostState {
    bool ready = false;
    const void* key[4] = {nullptr, nullptr, nullptr, nullptr};
    CUtensorMap mX[2], mRes[2], mW, mWr, mWo, mOut, mFin;
    bf16 *x1T, *x2T;
};

extern "C" void kernel_launch(void* const* d_in, const int* in_sizes, int n_in, void* d_out, int out_size) {
    const bf16* x = (const bf16*)d_in[0];
    const bf16* wqkv = (const bf16*)d_in[1];
    const bf16* wo = (const bf16*)d_in[2];
    const bf16* lar = (const bf16*)d_in[4];
    const bf16* aim = (const bf16*)d_in[5];
    const bf16* cre = (const bf16*)d_in[6];
    const bf16* cim = (const bf16*)d_in[7];
    const bf16* logdt = (const bf16*)d_in[8];
    const bf16* dskip = (const bf16*)d_in[9];
    static HostState hs;
    if (!hs.ready || hs.key[0] != wqkv || hs.key[1] != wo || hs.key[2] != x || hs.key[3] != d_out) {
        void* fn = nullptr;
        cudaDriverEntryPointQueryResult qr;
        cudaGetDriverEntryPoint("cuTensorMapEncodeTiled", &fn, cudaEnableDefault, &qr);
        EncodeTiledFn enc = (EncodeTiledFn)fn;
        cudaGetSymbolAddress((void**)&hs.x1T, g_x1T);
        cudaGetSymbolAddress((void**)&hs.x2T, g_x2T);
        {
            cuuint64_t d[3] = {DM, SEQ / 2, 2}, s[2] = {DM * 4, DM * 2};
            cuuint32_t b[3] = {64, 64, 2}, br[3] = {16, 64, 2};
            make_map(enc, &hs.mX[0], x, 3, d, s, b, CU_TENSOR_MAP_SWIZZLE_128B);
            make_map(enc, &hs.mRes[0], x, 3, d, s, br, CU_TENSOR_MAP_SWIZZLE_32B);
            cuuint64_t d2[3] = {SEQ / 2, DM, 2}, s2[2] = {XP * 2, SEQ};
            cuuint32_t b2[3] = {64, 80, 2};
            make_map(enc, &hs.mX[1], hs.x2T, 3, d2, s2, b, CU_TENSOR_MAP_SWIZZLE_128B);
            make_map(enc, &hs.mRes[1], hs.x2T, 3, d2, s2, b2, CU_TENSOR_MAP_SWIZZLE_128B);
            cuuint64_t d3[2] = {SEQ, DM};
            make_map(enc, &hs.mOut, hs.x1T, 2, d3, s2, b2, CU_TENSOR_MAP_SWIZZLE_128B);
        }
        { cuuint64_t d[2] = {3 * DM, DM}, s[1] = {3 * DM * 2}; cuuint32_t b[2] = {64, 32};
          make_map(enc, &hs.mW, wqkv, 2, d, s, b, CU_TENSOR_MAP_SWIZZLE_128B); }
        { cuuint64_t d[3] = {DM, DM, 3}, s[2] = {3 * DM * 2, DM * 2}; cuuint32_t b[3] = {16, 32, 3};
          make_map(enc, &hs.mWr, wqkv, 3, d, s, b, CU_TENSOR_MAP_SWIZZLE_32B); }
        { cuuint64_t d[4] = {8, 8, DM / 8, DM / 8}, s[3] = {DM * 2, 16, DM * 16}; cuuint32_t b[4] = {8, 8, 10, 5};
          make_map(enc, &hs.mWo, wo, 4, d, s, b, CU_TENSOR_MAP_SWIZZLE_NONE); }
        { cuuint64_t d[3] = {DM, SEQ / 16, 16}, s[2] = {DM * 32, DM * 2}; cuuint32_t b[3] = {80, 8, 16};
          make_map(enc, &hs.mFin, d_out, 3, d, s, b, CU_TENSOR_MAP_SWIZZLE_NONE); }
        cudaFuncSetAttribute(fused_kernel, cudaFuncAttributeMaxDynamicSharedMemorySize, Q_SMEM);
        hs.key[0] = wqkv; hs.key[1] = wo; hs.key[2] = x; hs.key[3] = d_out;
        hs.ready = true;
    }
    const SsmParams sp = {lar, aim, cre, cim, logdt, dskip};
    launch(fused_kernel, 128, 384, Q_SMEM, 2, false, sp, hs.mX[0], hs.mX[1], hs.mW, hs.mWr, hs.mRes[0], hs.mRes[1], hs.mOut, hs.mWo, hs.mFin);
}
```

```cpp
#include <cuda_runtime.h>
#include <cuda.h>
#include <cuda_bf16.h>
#include <cuda_fp16.h>
#include <stdint.h>

typedef __nv_bfloat16 bf16;

constexpr int SEQ = 2048;
constexpr int DM  = 640;
constexpr int XP  = SEQ + 64;
constexpr int NMODE = 192;

__device__ __forceinline__ uint32_t s2u(const void* p) { return (uint32_t)__cvta_generic_to_shared(p); }
__device__ __forceinline__ void mbar_init(uint32_t b, int c) { asm volatile("mbarrier.init.shared::cta.b64 [%0], %1;" ::"r"(b), "r"(c)); }
__device__ __forceinline__ void mbar_expect(uint32_t b, uint32_t bytes) { asm volatile("mbarrier.arrive.expect_tx.shared::cta.b64 _, [%0], %1;" ::"r"(b), "r"(bytes) : "memory"); }
__device__ __forceinline__ void mbar_arrive(uint32_t b) { asm volatile("mbarrier.arrive.shared::cta.b64 _, [%0];" ::"r"(b) : "memory"); }
__device__ __forceinline__ void mbar_arrive_cta(uint32_t b, uint32_t cta) {
    asm volatile("{\n.reg .b32 ra;\nmapa.shared::cluster.u32 ra, %0, %1;\nmbarrier.arrive.shared::cluster.b64 _, [ra];\n}" ::"r"(b), "r"(cta) : "memory");
}
__device__ __forceinline__ void mbar_wait(uint32_t b, uint32_t ph) {
#ifdef M_PLAIN
    asm volatile("{\n.reg .pred p;\nW: mbarrier.try_wait.parity.shared::cta.b64 p, [%0], %1;\n@!p bra W;\n}" ::"r"(b), "r"(ph) : "memory");
    return;
#endif
    asm volatile("{\n.reg .pred p;\n.reg .u32 n;\nmbarrier.try_wait.parity.shared::cta.b64 p, [%0], %1;\n@p bra D;\nmov.u32 n, 0;\n"
                 "W: mbarrier.try_wait.parity.shared::cta.b64 p, [%0], %1;\n@p bra D;\nadd.u32 n, n, 1;\nsetp.lt.u32 p, n, 4194304;\n@p bra W;\ntrap;\nD:\n}"
                 ::"r"(b), "r"(ph) : "memory");
}
__device__ __forceinline__ void fence_mbar_init() { asm volatile("fence.mbarrier_init.release.cluster;" ::: "memory"); }
__device__ __forceinline__ void cluster_sync() { asm volatile("barrier.cluster.arrive.aligned;\nbarrier.cluster.wait.aligned;" ::: "memory"); }
__device__ __forceinline__ void pdl_wait() { asm volatile("griddepcontrol.wait;" ::: "memory"); }
__device__ __forceinline__ void pdl_launch() { asm volatile("griddepcontrol.launch_dependents;" ::: "memory"); }
__device__ __forceinline__ void named_bar(int id, int n) { asm volatile("bar.sync %0, %1;" ::"r"(id), "r"(n) : "memory"); }
__device__ __forceinline__ void fence_async_smem() { asm volatile("fence.proxy.async.shared::cta;" ::: "memory"); }

__device__ __forceinline__ void tma2d(uint32_t dst, const CUtensorMap* m, int c0, int c1, uint32_t bar) {
    asm volatile("cp.async.bulk.tensor.2d.shared::cluster.global.mbarrier::complete_tx::bytes [%0], [%1, {%3, %4}], [%2];"
                 ::"r"(dst), "l"(m), "r"(bar), "r"(c0), "r"(c1) : "memory");
}
__device__ __forceinline__ void tma2d_mc(uint32_t dst, const CUtensorMap* m, int c0, int c1, uint32_t bar, uint16_t mask) {
    asm volatile("cp.async.bulk.tensor.2d.shared::cluster.global.mbarrier::complete_tx::bytes.multicast::cluster [%0], [%1, {%3, %4}], [%2], %5;"
                 ::"r"(dst), "l"(m), "r"(bar), "r"(c0), "r"(c1), "h"(mask) : "memory");
}
__device__ __forceinline__ void tma3d(uint32_t dst, const CUtensorMap* m, int c0, int c1, int c2, uint32_t bar) {
    asm volatile("cp.async.bulk.tensor.3d.shared::cluster.global.mbarrier::complete_tx::bytes [%0], [%1, {%3, %4, %5}], [%2];"
                 ::"r"(dst), "l"(m), "r"(bar), "r"(c0), "r"(c1), "r"(c2) : "memory");
}
__device__ __forceinline__ void tma3d_mc(uint32_t dst, const CUtensorMap* m, int c0, int c1, int c2, uint32_t bar, uint16_t mask) {
    asm volatile("cp.async.bulk.tensor.3d.shared::cluster.global.mbarrier::complete_tx::bytes.multicast::cluster [%0], [%1, {%3, %4, %5}], [%2], %6;"
                 ::"r"(dst), "l"(m), "r"(bar), "r"(c0), "r"(c1), "r"(c2), "h"(mask) : "memory");
}
__device__ __forceinline__ void bulk_g2s(uint32_t dst, const void* src, uint32_t bytes, uint32_t bar) {
    asm volatile("cp.async.bulk.shared::cluster.global.mbarrier::complete_tx::bytes [%0], [%1], %2, [%3];"
                 ::"r"(dst), "l"(src), "r"(bytes), "r"(bar) : "memory");
}
__device__ __forceinline__ void bulk_g2s_mc(uint32_t dst, const void* src, uint32_t bytes, uint32_t bar, uint16_t mask) {
    asm volatile("cp.async.bulk.shared::cluster.global.mbarrier::complete_tx::bytes.multicast::cluster [%0], [%1], %2, [%3], %4;"
                 ::"r"(dst), "l"(src), "r"(bytes), "r"(bar), "h"(mask) : "memory");
}
__device__ __forceinline__ void prefetch_l2(const void* p, uint32_t bytes) { asm volatile("cp.async.bulk.prefetch.L2.global [%0], %1;" ::"l"(p), "r"(bytes) : "memory"); }
__device__ __forceinline__ void prefetch_tmap(const CUtensorMap* m) { asm volatile("prefetch.tensormap [%0];" ::"l"(m) : "memory"); }

__device__ __forceinline__ void wg_fence() { asm volatile("wgmma.fence.sync.aligned;" ::: "memory"); }
__device__ __forceinline__ void wg_commit() { asm volatile("wgmma.commit_group.sync.aligned;" ::: "memory"); }
template <int N> __device__ __forceinline__ void wg_wait() { asm volatile("wgmma.wait_group.sync.aligned %0;" ::"n"(N) : "memory"); }
__device__ __forceinline__ uint64_t mkdesc(uint32_t addr, uint32_t lbo, uint32_t sbo, uint32_t mode) {
    return (uint64_t)((addr & 0x3FFFF) >> 4) | ((uint64_t)(lbo >> 4) << 16) | ((uint64_t)(sbo >> 4) << 32) | ((uint64_t)mode << 62);
}

__device__ __forceinline__ void mma16816(float (&c)[4], uint32_t a0, uint32_t a1, uint32_t a2, uint32_t a3, uint32_t b0, uint32_t b1) {
    asm("mma.sync.aligned.m16n8k16.row.col.f32.bf16.bf16.f32 {%0,%1,%2,%3},{%4,%5,%6,%7},{%8,%9},{%0,%1,%2,%3};"
                 : "+f"(c[0]), "+f"(c[1]), "+f"(c[2]), "+f"(c[3]) : "r"(a0), "r"(a1), "r"(a2), "r"(a3), "r"(b0), "r"(b1));
}
__device__ __forceinline__ void mma1688(float (&c)[4], uint32_t a0, uint32_t a1, uint32_t b0) {
    asm("mma.sync.aligned.m16n8k8.row.col.f32.bf16.bf16.f32 {%0,%1,%2,%3},{%4,%5},{%6},{%0,%1,%2,%3};"
                 : "+f"(c[0]), "+f"(c[1]), "+f"(c[2]), "+f"(c[3]) : "r"(a0), "r"(a1), "r"(b0));
}
__device__ __forceinline__ void ldsm_x4(uint32_t& r0, uint32_t& r1, uint32_t& r2, uint32_t& r3, uint32_t a) {
    asm volatile("ldmatrix.sync.aligned.m8n8.x4.shared.b16 {%0,%1,%2,%3}, [%4];" : "=r"(r0), "=r"(r1), "=r"(r2), "=r"(r3) : "r"(a) : "memory");
}
__device__ __forceinline__ void ldsm_x4_t(uint32_t& r0, uint32_t& r1, uint32_t& r2, uint32_t& r3, uint32_t a) {
    asm volatile("ldmatrix.sync.aligned.m8n8.x4.trans.shared.b16 {%0,%1,%2,%3}, [%4];" : "=r"(r0), "=r"(r1), "=r"(r2), "=r"(r3) : "r"(a) : "memory");
}
__device__ __forceinline__ void ldsm_x2(uint32_t& r0, uint32_t& r1, uint32_t a) {
    asm volatile("ldmatrix.sync.aligned.m8n8.x2.shared.b16 {%0,%1}, [%2];" : "=r"(r0), "=r"(r1) : "r"(a) : "memory");
}
__device__ __forceinline__ void ldsm_x2_t(uint32_t& r0, uint32_t& r1, uint32_t a) {
    asm volatile("ldmatrix.sync.aligned.m8n8.x2.trans.shared.b16 {%0,%1}, [%2];" : "=r"(r0), "=r"(r1) : "r"(a) : "memory");
}
__device__ __forceinline__ void stsm_x4(uint32_t a, uint32_t r0, uint32_t r1, uint32_t r2, uint32_t r3) {
    asm volatile("stmatrix.sync.aligned.m8n8.x4.shared.b16 [%0], {%1,%2,%3,%4};" ::"r"(a), "r"(r0), "r"(r1), "r"(r2), "r"(r3) : "memory");
}
__device__ __forceinline__ void stsm_x4_t(uint32_t a, uint32_t r0, uint32_t r1, uint32_t r2, uint32_t r3) {
    asm volatile("stmatrix.sync.aligned.m8n8.x4.trans.shared.b16 [%0], {%1,%2,%3,%4};" ::"r"(a), "r"(r0), "r"(r1), "r"(r2), "r"(r3) : "memory");
}
__device__ __forceinline__ void stsm_x2(uint32_t a, uint32_t r0, uint32_t r1) {
    asm volatile("stmatrix.sync.aligned.m8n8.x2.shared.b16 [%0], {%1,%2};" ::"r"(a), "r"(r0), "r"(r1) : "memory");
}
__device__ __forceinline__ uint32_t movm_t(uint32_t a) {
    uint32_t d;
    asm volatile("movmatrix.sync.aligned.m8n8.trans.b16 %0, %1;" : "=r"(d) : "r"(a));
    return d;
}
__device__ __forceinline__ uint32_t lds32(uint32_t a) { uint32_t v; asm volatile("ld.shared.u32 %0, [%1];" : "=r"(v) : "r"(a) : "memory"); return v; }
__device__ __forceinline__ uint32_t ldsv32(uint32_t a) { uint32_t v; asm volatile("ld.volatile.shared.u32 %0, [%1];" : "=r"(v) : "r"(a) : "memory"); return v; }
__device__ __forceinline__ void sts32(uint32_t a, uint32_t v) { asm volatile("st.shared.u32 [%0], %1;" ::"r"(a), "r"(v) : "memory"); }
__device__ __forceinline__ uint4 lds128(uint32_t a) { uint4 v; asm volatile("ld.shared.v4.u32 {%0,%1,%2,%3}, [%4];" : "=r"(v.x), "=r"(v.y), "=r"(v.z), "=r"(v.w) : "r"(a) : "memory"); return v; }
__device__ __forceinline__ void sts128(uint32_t a, uint4 v) { asm volatile("st.shared.v4.u32 [%0], {%1,%2,%3,%4};" ::"r"(a), "r"(v.x), "r"(v.y), "r"(v.z), "r"(v.w) : "memory"); }

__device__ __forceinline__ void stg128(void* p, uint4 v) { asm volatile("st.global.v4.u32 [%0], {%1,%2,%3,%4};" ::"l"(p), "r"(v.x), "r"(v.y), "r"(v.z), "r"(v.w) : "memory"); }

__device__ __forceinline__ uint4 ldg128(const void* p) { uint4 v; asm volatile("ld.global.v4.u32 {%0,%1,%2,%3}, [%4];" : "=r"(v.x), "=r"(v.y), "=r"(v.z), "=r"(v.w) : "l"(p) : "memory"); return v; }
__device__ __forceinline__ uint2 ldg64(const void* p) { uint2 v; asm volatile("ld.global.v2.u32 {%0,%1}, [%2];" : "=r"(v.x), "=r"(v.y) : "l"(p) : "memory"); return v; }
__device__ __forceinline__ uint32_t ldg32(const void* p) { uint32_t v; asm volatile("ld.global.u32 %0, [%1];" : "=r"(v) : "l"(p) : "memory"); return v; }

__device__ __forceinline__ uint32_t pack2(float lo, float hi) {
    uint32_t r;
    asm("cvt.rn.bf16x2.f32 %0, %1, %2;" : "=r"(r) : "f"(hi), "f"(lo));
    return r;
}
__device__ __forceinline__ float bf_lo(uint32_t v) { return __uint_as_float(v << 16); }
__device__ __forceinline__ float bf_hi(uint32_t v) { return __uint_as_float(v & 0xFFFF0000u); }
__device__ __forceinline__ float rbf(float x) { return __uint_as_float(pack2(0.f, x) & 0xFFFF0000u); }
__device__ __forceinline__ float ex2(float x) { float r; asm("ex2.approx.ftz.f32 %0, %1;" : "=f"(r) : "f"(x)); return r; }

__device__ __forceinline__ float2 ln_finish(float sum, float sumsq) {
    const float m = sum * (1.0f / DM);
    const float v = fmaxf(fmaf(sumsq, 1.0f / DM, -m * m), 0.f);
    float s, r;
    asm("sqrt.approx.ftz.f32 %0, %1;" : "=f"(s) : "f"(rbf(rbf(v) + 1e-5f)));
    asm("rcp.approx.ftz.f32 %0, %1;" : "=f"(r) : "f"(rbf(s)));
    return make_float2(m, r);
}
__device__ __forceinline__ uint32_t ln_finish_packed(float sum, float sumsq) {
    const float m = sum * (1.0f / DM);
    const float v = fmaxf(fmaf(sumsq, 1.0f / DM, -m * m), 0.f);
    float s;
    asm("sqrt.approx.ftz.f32 %0, %1;" : "=f"(s) : "f"(rbf(rbf(v) + 1e-5f)));
    return pack2(s, m);
}
__device__ __forceinline__ float frsq(float x) { float r; asm("rsqrt.approx.ftz.f32 %0, %1;" : "=f"(r) : "f"(x)); return r; }
__device__ __forceinline__ float frcp(float x) { float r; asm("rcp.approx.ftz.f32 %0, %1;" : "=f"(r) : "f"(x)); return r; }
__device__ __forceinline__ bool elect_one() {
    uint32_t p;
    asm volatile("{\n.reg .pred p;\nelect.sync _|p, 0xffffffff;\nselp.u32 %0, 1, 0, p;\n}" : "=r"(p));
    return p != 0;
}
__device__ __forceinline__ void cluster_arrive_relaxed() { asm volatile("barrier.cluster.arrive.relaxed.aligned;" ::: "memory"); }
__device__ __forceinline__ void cluster_wait() { asm volatile("barrier.cluster.wait.aligned;" ::: "memory"); }
__device__ __forceinline__ unsigned long long ld_ll(const unsigned long long* p) {
    unsigned long long v;
    asm volatile("ld.relaxed.gpu.global.b64 %0, [%1];" : "=l"(v) : "l"(p) : "memory");
    return v;
}
__device__ __forceinline__ void st_ll(unsigned long long* p, uint32_t payload, uint32_t tag) {
    const unsigned long long v = (unsigned long long)payload | ((unsigned long long)tag << 32);
    asm volatile("st.relaxed.gpu.global.b64 [%0], %1;" ::"l"(p), "l"(v) : "memory");
}
__device__ __forceinline__ uint4 ld_ll4(const uint4* p) {
    uint4 v;
    asm volatile("{\n.reg .b128 t;\n.reg .b64 a, b;\nld.relaxed.gpu.global.b128 t, [%4];\nmov.b128 {a, b}, t;\nmov.b64 {%0, %1}, a;\nmov.b64 {%2, %3}, b;\n}"
                 : "=r"(v.x), "=r"(v.y), "=r"(v.z), "=r"(v.w) : "l"(p) : "memory");
    return v;
}
__device__ __forceinline__ void st_ll4(uint4* p, uint32_t x, uint32_t y, uint32_t z, uint32_t w) {
    asm volatile("{\n.reg .b128 t;\n.reg .b64 a, b;\nmov.b64 a, {%1, %2};\nmov.b64 b, {%3, %4};\nmov.b128 t, {a, b};\nst.relaxed.gpu.global.b128 [%0], t;\n}"
                 ::"l"(p), "r"(x), "r"(y), "r"(z), "r"(w) : "memory");
}

__device__ __forceinline__ void bulk_s2g(void* dst, uint32_t src, uint32_t bytes) {
    asm volatile("cp.async.bulk.global.shared::cta.bulk_group [%0], [%1], %2;" ::"l"(dst), "r"(src), "r"(bytes) : "memory");
}
__device__ __forceinline__ void bulk_commit() { asm volatile("cp.async.bulk.commit_group;" ::: "memory"); }
__device__ __forceinline__ void bulk_wait() { asm volatile("cp.async.bulk.wait_group 0;" ::: "memory"); }
__device__ __forceinline__ void fence_async_global() { asm volatile("fence.proxy.async.global;" ::: "memory"); }
__device__ __forceinline__ void fence_release() { asm volatile("fence.release.gpu;" ::: "memory"); }
__device__ __forceinline__ void fence_acquire() { asm volatile("fence.acquire.gpu;" ::: "memory"); }
template<int TA, int TB>
__device__ __forceinline__ void wgmma_n192(float (&d)[96], uint64_t da, uint64_t db, int scale_d) {
  asm volatile("{\n.reg .pred p;\nsetp.ne.b32 p, %98, 0;\n"
    "wgmma.mma_async.sync.aligned.m64n192k16.f32.bf16.bf16 "
    "{%0, %1, %2, %3, %4, %5, %6, %7, %8, %9, %10, %11, %12, %13, %14, %15, %16, %17, %18, %19, %20, %21, %22, %23, %24, %25, %26, %27, %28, %29, %30, %31, %32, %33, %34, %35, %36, %37, %38, %39, %40, %41, %42, %43, %44, %45, %46, %47, %48, %49, %50, %51, %52, %53, %54, %55, %56, %57, %58, %59, %60, %61, %62, %63, %64, %65, %66, %67, %68, %69, %70, %71, %72, %73, %74, %75, %76, %77, %78, %79, %80, %81, %82, %83, %84, %85, %86, %87, %88, %89, %90, %91, %92, %93, %94, %95}, %96, %97, p, 1, 1, %99, %100;\n}\n"
    : "+f"(d[0]), "+f"(d[1]), "+f"(d[2]), "+f"(d[3]), "+f"(d[4]), "+f"(d[5]), "+f"(d[6]), "+f"(d[7]), "+f"(d[8]), "+f"(d[9]), "+f"(d[10]), "+f"(d[11]), "+f"(d[12]), "+f"(d[13]), "+f"(d[14]), "+f"(d[15]), "+f"(d[16]), "+f"(d[17]), "+f"(d[18]), "+f"(d[19]), "+f"(d[20]), "+f"(d[21]), "+f"(d[22]), "+f"(d[23]), "+f"(d[24]), "+f"(d[25]), "+f"(d[26]), "+f"(d[27]), "+f"(d[28]), "+f"(d[29]), "+f"(d[30]), "+f"(d[31]), "+f"(d[32]), "+f"(d[33]), "+f"(d[34]), "+f"(d[35]), "+f"(d[36]), "+f"(d[37]), "+f"(d[38]), "+f"(d[39]), "+f"(d[40]), "+f"(d[41]), "+f"(d[42]), "+f"(d[43]), "+f"(d[44]), "+f"(d[45]), "+f"(d[46]), "+f"(d[47]), "+f"(d[48]), "+f"(d[49]), "+f"(d[50]), "+f"(d[51]), "+f"(d[52]), "+f"(d[53]), "+f"(d[54]), "+f"(d[55]), "+f"(d[56]), "+f"(d[57]), "+f"(d[58]), "+f"(d[59]), "+f"(d[60]), "+f"(d[61]), "+f"(d[62]), "+f"(d[63]), "+f"(d[64]), "+f"(d[65]), "+f"(d[66]), "+f"(d[67]), "+f"(d[68]), "+f"(d[69]), "+f"(d[70]), "+f"(d[71]), "+f"(d[72]), "+f"(d[73]), "+f"(d[74]), "+f"(d[75]), "+f"(d[76]), "+f"(d[77]), "+f"(d[78]), "+f"(d[79]), "+f"(d[80]), "+f"(d[81]), "+f"(d[82]), "+f"(d[83]), "+f"(d[84]), "+f"(d[85]), "+f"(d[86]), "+f"(d[87]), "+f"(d[88]), "+f"(d[89]), "+f"(d[90]), "+f"(d[91]), "+f"(d[92]), "+f"(d[93]), "+f"(d[94]), "+f"(d[95])
    : "l"(da), "l"(db), "r"(scale_d), "n"(TA), "n"(TB));
}

template<int TA, int TB>
__device__ __forceinline__ void wgmma_n48(float (&d)[24], uint64_t da, uint64_t db, int scale_d) {
  asm volatile("{\n.reg .pred p;\nsetp.ne.b32 p, %26, 0;\n"
    "wgmma.mma_async.sync.aligned.m64n48k16.f32.bf16.bf16 "
    "{%0, %1, %2, %3, %4, %5, %6, %7, %8, %9, %10, %11, %12, %13, %14, %15, %16, %17, %18, %19, %20, %21, %22, %23}, %24, %25, p, 1, 1, %27, %28;\n}\n"
    : "+f"(d[0]), "+f"(d[1]), "+f"(d[2]), "+f"(d[3]), "+f"(d[4]), "+f"(d[5]), "+f"(d[6]), "+f"(d[7]), "+f"(d[8]), "+f"(d[9]), "+f"(d[10]), "+f"(d[11]), "+f"(d[12]), "+f"(d[13]), "+f"(d[14]), "+f"(d[15]), "+f"(d[16]), "+f"(d[17]), "+f"(d[18]), "+f"(d[19]), "+f"(d[20]), "+f"(d[21]), "+f"(d[22]), "+f"(d[23])
    : "l"(da), "l"(db), "r"(scale_d), "n"(TA), "n"(TB));
}

__device__ __forceinline__ void wgmma_rs80(float (&d)[40], const uint4& a, uint64_t db, int scale_d) {
  asm volatile("{\n.reg .pred p;\nsetp.ne.b32 p, %45, 0;\n"
    "wgmma.mma_async.sync.aligned.m64n80k16.f32.bf16.bf16 {%0,%1,%2,%3,%4,%5,%6,%7,%8,%9,%10,%11,%12,%13,%14,%15,%16,%17,%18,%19,%20,%21,%22,%23,%24,%25,%26,%27,%28,%29,%30,%31,%32,%33,%34,%35,%36,%37,%38,%39}, {%40,%41,%42,%43}, %44, p, 1, 1, 1;\n}\n"
    : "+f"(d[0]), "+f"(d[1]), "+f"(d[2]), "+f"(d[3]), "+f"(d[4]), "+f"(d[5]), "+f"(d[6]), "+f"(d[7]), "+f"(d[8]), "+f"(d[9]), "+f"(d[10]), "+f"(d[11]), "+f"(d[12]), "+f"(d[13]), "+f"(d[14]), "+f"(d[15]), "+f"(d[16]), "+f"(d[17]), "+f"(d[18]), "+f"(d[19]), "+f"(d[20]), "+f"(d[21]), "+f"(d[22]), "+f"(d[23]), "+f"(d[24]), "+f"(d[25]), "+f"(d[26]), "+f"(d[27]), "+f"(d[28]), "+f"(d[29]), "+f"(d[30]), "+f"(d[31]), "+f"(d[32]), "+f"(d[33]), "+f"(d[34]), "+f"(d[35]), "+f"(d[36]), "+f"(d[37]), "+f"(d[38]), "+f"(d[39])
    : "r"(a.x), "r"(a.y), "r"(a.z), "r"(a.w), "l"(db), "r"(scale_d));
}

__device__ const __align__(1024) uint32_t c_fft[11264] = {
0x2ddc2dba,0x2fe62eb5,0x2ed02eb5,0xafffaf6e,0x2e1f2dfe,0x2e3f2fbc,0x2f022ee9,0xad27af30,0x2e5e2e3f,0x1fd92b5e,0x2f302f1a,0x244ea875,0x2e992e7c,0xad96a993,0x2f5a2f46,0x2e992c32,
0xad00ad72,0xa17eac32,0xa17ea515,0xabb79cb6,0xac07ac87,0x2dfe29f1,0x1fd99648,0xafedae99,0xa9f1ab05,0x2fd42fbc,0x26a1244e,0xad96af91,0xa765a8d5,0x2aaa2e3f,0x29932875,0x2515a8d5,
0xae99adfe,0xb000aee9,0xaf6eafbc,0x2c872f30,0xaf80af1a,0xac32af02,0xae7caf02,0xaaaa217e,0xaff4afc9,0x2b5e9cb6,0xad27addc,0xaff4ae7c,0xafedb000,0x2ffc2eb5,0xab05ac5d,0xacd8af5a,
0x2c072d27,0x9fd92bb7,0xadfead00,0x2fed2e1f,0x25db2993,0xaf6eacb0,0xaf6eaed0,0x2c5d2f46,0xa5151648,0xaddcafdd,0xafffafd4,0xac321648,0xabb7a934,0x28d5a814,0xafa0afed,0xaff4af30,
0x2f302e3f,0x2fed2f1a,0x28142b5e,0x2934a875,0x30002fc9,0x26a12ddc,0xa5db1cb6,0x30002e7c,0x2f462fd4,0xaed0aa4e,0xacb0aa4e,0x29932e99,0x2d272e5e,0xae3faffc,0xaf02adfe,0xae1fa814,
0xa9f1acd8,0x26a1ab05,0x2fd42ffc,0xad96afed,0x2515a30e,0x2fff2e1f,0x2ddc2f1a,0x2c32a30e,0x2d272aaa,0x28752e7c,0x28752c32,0x2fa02f80,0x2f912e99,0xaee9a9f1,0xa8141648,0x9fd92c87,
0xafa0ae7c,0xafafaf46,0x2d002993,0xafa0ac32,0xaf91b000,0x244eac5d,0x2fbc2eb5,0xab05af5a,0xac87ae5e,0x30002dfe,0x2f6e2ffc,0x2e992814,0x1cb6a875,0x25152e1f,0x2c322e1f,0x2d722ff4,
0x27652c87,0xa9932a4e,0xaaaaadba,0xa5152c87,0xabb7a44e,0xafa0af30,0x28d59fd9,0xaff4ae5e,0xaf91ae1f,0x2814abb7,0x2ee92d00,0x1fd9ad27,0xaf5aafff,0x2fd42ed0,0x2fd42fe6,0x30002ddc,
0x2f462f6e,0x2c322fdd,0x2e7c2fdd,0xa993b000,0xab5e2934,0xafafacd8,0xad00244e,0x2f1a2dfe,0xaee9afaf,0x2f30a17e,0xadfeaff8,0xafbca30e,0x2c5da765,0xa9f12ddc,0x2d969cb6,0x2c5dacb0,
0x2bb7a993,0x2f1aa515,0x2f1a2765,0xaff4aaaa,0x2e5e2fd4,0xab052dba,0x29342f6e,0x2ee9a6a1,0xadba1fd9,0xa5dbafed,0xafddac07,0xaa4e2dfe,0xacb0aff8,0x2ddc2f02,0x9cb6ae3f,0xa765aff8,
0xaeb5af91,0xaa4eafed,0x9648ae5e,0xac5d2d4d,0x2ddca17e,0x2e7c2e3f,0x2fc92e3f,0x1cb6afa0,0x2bb72fe6,0xaff8a993,0xab5e2aaa,0x2bb72fc9,0xafbcaa4e,0x2f30a5db,0xadfeafdd,0xaee9adba,
0xacd828d5,0xaf91230e,0xaf30af02,0x2c072fa0,0xac5dafff,0x2dbaac32,0x2dbaa515,0xae99addc,0x2fc929f1,0xa9932eb5,0x2aaa2fdd,0x2fe629f1,0xa30e2dfe,0xa17eafed,0xaff8ac07,0xafaf1fd9,
0x2dfe2faf,0x28142ff8,0xae5e217e,0x2ffc230e,0xaf5aa515,0xac87af46,0xa6a1af80,0xaf5a2765,0x1cb6ae99,0x2e7c2dba,0x2fc92dba,0x2ddcac5d,0x2f1a2ee9,0xafafab05,0xad002934,0xab5e2e5e,
0x2dbaa814,0x2fdd9fd9,0x25db2f91,0x2a4eaee9,0x27652faf,0xaf4628d5,0xaf80ae1f,0xa5152faf,0xafa0addc,0x2e3fac32,0x2e3fa515,0xa17eafff,0x2dfea6a1,0xacd82dba,0x244e2f6e,0x29342fd4,
0xad27afc9,0xa30eafff,0x2faf2d72,0xad27ae7c,0x2ffc2a4e,0x28142fdd,0xae5e25db,0x2dfe2dba,0xac5d2c07,0xaa4eaf91,0x9648af30,0xaeb5acd8,0xa993aff4,0x2c322f1a,0x2e7c2f1a,0x2f462bb7,
0xae7c26a1,0xafff1648,0x2d72aa4e,0xafc926a1,0x230eaee9,0x2ff89fd9,0x217e2f91,0x2fafa814,0x2d4d2fa0,0xafed230e,0xae5eaf02,0xaf9128d5,0xb000aaaa,0x2fdda515,0x2fdd2765,0x2f6ea993,
0x9cb63000,0xacb02fd4,0xa7652fd4,0x2ddcaf5a,0x217eaffc,0x2ff4ac07,0x2875afbc,0xaff82934,0xa44e2ff4,0xadfea8d5,0xa9342fa0,0x2cd82bb7,0x25dbafe6,0x16482f46,0x29f1af80,0x25dbafc9,
0x2ff41cb6,0x2e1f2765,0x2e1f2cb0,0xa875addc,0xafbca5db,0x1fd9af5a,0xad4dad96,0xacd82fdd,0x2f5a2934,0xaeb52ee9,0x2c5d2e5e,0x3000ab05,0xaed0ab5e,0x2f80a30e,0xaaaaaf02,0xacb0ab5e,
0x25dbaffc,0x2d96afbc,0x2f5aac07,0xafdd2934,0xaaaa2fa0,0xafc92875,0xafe62875,0x29932d27,0x2d00aed0,0x28d52d72,0x2ff89cb6,0x2d00afe6,0xae5e2d96,0x2d4dafd4,0xaf91a6a1,0xafed29f1,
0xafbca17e,0xad4da875,0x1fd9aff4,0xacd82ff8,0x2e992aaa,0xaa4e2fe6,0xaa4e2fc9,0x2fd4a993,0xacb0ad96,0x2fffac87,0x2d72aeb5,0xa765ad96,0x28752f30,0xab5eac07,0xaf1a2cd8,0xae3f2f91,
0xa9342ff4,0xae5e2fa0,0xaee9a8d5,0x2b052bb7,0x2d96aed0,0x2eb59cb6,0x2c872d72,0x2d96afe6,0xaf802c5d,0x2765af6e,0xa515af6e,0xaf4625db,0x2ff8a44e,0xaff42d4d,0xa8752ffc,0xa17e2ee9,
0x2f5a244e,0x2c5d2934,0xaeb52dfe,0x3000acd8,0xacb0ad00,0x2d72aff8,0x2fffa8d5,0xa765ad00,0x217e2f80,0xaf022515,0xaf02a765,0xaf1a2f46,0x2b05afdd,0xa8142f5a,0x2c072d96,0x2d4d25db,
0x2b5eafe6,0x2f02af80,0x230e2f46,0x2b5eafc9,0xaf302d96,0xacd8a6a1,0x2c07afd4,0xaf9129f1,0x2fdda44e,0xad962ffc,0xaf5a2d4d,0xa5db2ee9,0xad72abb7,0x2e7ca17e,0x2fc9a17e,0x2fffad00,
0xaed0a5db,0xaaaaa9f1,0x2f809648,0xacb0a5db,0x28752e5e,0xaf1a2f91,0xab5ead4d,0xae3f2fed,0x2b05aff8,0x2c072875,0xa8142ff4,0x2d4d217e,0xaf6e2d72,0x2eb5afc9,0x2eb5ae7c,0x2dbaafff,
0xaf802f5a,0xafc92e99,0xafe62e99,0x2f46ad96,0x28d52b05,0xaf022fed,0x230e2cd8,0x2fa0affc,0x2fbcaf02,0xa9342d27,0x2ffcae1f,0x2c07ae3f,0xa6a1ac32,0x2a4e9cb6,0x9648ad72,0xa6a1a515,
0x28752aaa,0xa8d52cb0,0xa8d52ed0,0x2e3faf80,0x2fedaeb5,0x29349648,0x2f30aa4e,0x2814ac5d,0x1648ad4d,0x2e99acd8,0x2c87afbc,0xa9f11fd9,0xafe62d27,0x2fffafaf,0xaddc230e,0xaed02d27,
0x2fd4af30,0x2f6eae5e,0x2dbaa44e,0xa6a19fd9,0x1cb6ad27,0x2fe6aff4,0x2ed0aff4,0xad722b5e,0xafaf2cb0,0x2e1faf46,0xa8d5a993,0xafaf2ed0,0xac072f6e,0x2934ac87,0xaffc2e99,0xafbc3000,
0xa44eab5e,0x2b05ad00,0x2f91afaf,0xafbc2f1a,0xafd42d72,0x1648a765,0x1648acb0,0xafdd2fff,0xac322f5a,0xaaaa26a1,0xaf802c87,0xae7c2f5a,0x2d009fd9,0xae1f2cd8,0xad272fbc,0xabb72d4d,
0xaffc2f02,0xaee92e1f,0x244ead27,0xad4d2e3f,0xa9f12e7c,0xafdd2f80,0xaeb52aaa,0xa9f12c32,0x2d72a5db,0xafe63000,0xaed03000,0x9cb626a1,0x2fa0afbc,0xaf022f91,0x230e2b05,0x28d5a44e,
0x96482c07,0xac872d4d,0xae992b05,0x29f1a814,0x2ed0abb7,0xa9932b5e,0xaf462ff8,0x2cb0abb7,0x2f1aafff,0xa30e2765,0xa30e2cb0,0x2e1fad72,0x1fd9ac5d,0x244e9648,0x2e5eaa4e,0x2f30aeb5,
0x2ff8aed0,0x2e3faddc,0xaf022fff,0x2ff8afe6,0x2d4daf6e,0x2ee9ae99,0xa44e2c87,0x2ffcb000,0xa6a1a814,0x2f6eaf30,0x2dbaa934,0x2fd4afed,0xaf462d00,0x2fc9afa0,0x2fe6afa0,0x2f80afaf,
0x2515ac5d,0x2d72ad96,0x1cb629f1,0x2c32ac5d,0xad002814,0x2d27ad4d,0x2e1fab05,0x2bb7ac07,0xaffc2f1a,0x2cd8ad00,0x2fedafaf,0x2b05ab5e,0xadba2f80,0x2c87acb0,0x2c87aed0,0x2a4eaaaa,
0x2f802f6e,0x2fc92fdd,0x2fe62fdd,0xaf46b000,0x2fa02f91,0x2bb72e5e,0x2ff42fed,0xa8d5ad4d,0x2fbc2faf,0xa934217e,0x2ffc2ff8,0x2c07230e,0x2fd42fc9,0xaf5aad72,0x30002fff,0x2fd42e7c,
0x2bb72aaa,0x2f1a2cb0,0x2f1a2ed0,0xaff4af80,0x2cd82c5d,0x2f303000,0x2f912f5a,0xac07aeb5,0x2dba2d4d,0x25db2cd8,0x2fdd2fbc,0x2a4e9fd9,0x2e7c2e1f,0xad72a875,0x2fff2ff4,0x2fc92e1f,
0xa6a1a934,0x29f1a44e,0x2d962cd8,0xafd4adfe,0x1cb6a17e,0x2fe62e3f,0x2ed02e3f,0xad72afa0,0x28752515,0x2d272f80,0x2fa02f46,0x2875a765,0x2c072a4e,0xa93425db,0x2ffc2fdd,0x2fbc2dba,
0xae5eaf1a,0xa934ae3f,0x2b052875,0xaee9ab5e,0xac5dad72,0x2dba2765,0x2dba2cb0,0xae99afff,0xa765aa4e,0x2f802fd4,0x2f462e99,0x2515aa4e,0x230e9fd9,0x217e2cd8,0x2ff82fbc,0x2faf2d4d,
0xaffcafaf,0xaee9aff8,0x244ea17e,0xad4da30e,0xaf6eafe6,0x25dbaaaa,0x2c5d2993,0xaf6eafc9,0xad72ae99,0x2fe62dba,0x2ed02dba,0x1cb6ac5d,0xa8d5ac07,0x2bb72f30,0x2ff42f91,0x2fa02cd8,
0xadbaac07,0xafddad4d,0xa5dbab05,0xaa4e2814,0xafc9af02,0xaaaaaf1a,0x2993217e,0xafe6af02,0xafa0afff,0x2e3f2765,0x2e3f2cb0,0xa17ead72,0xad4daeb5,0x2e5e3000,0x2fed2f5a,0x2f912c5d,
0xa17e2765,0xad001cb6,0xabb7addc,0xa17e2cb0,0xad4daa4e,0xaee9afdd,0x244ea5db,0xaffcadba,0xafd4aee9,0x29f1a934,0x2d962b05,0xa6a1ae5e,0xaf46aff4,0x2fc92f1a,0x2fe62f1a,0x2f802bb7,
0x2cb02eb5,0x1cb62dba,0xaddcaf6e,0x27652eb5,0xa30e2814,0xaff8ad4d,0xa17eab05,0xafafac07,0xadfeab5e,0xa44eae3f,0x2cd82875,0xa934af1a,0xb000af80,0x2fdd2cb0,0x2fdd2ed0,0x2f6e2aaa,
0x2d723000,0x25152fd4,0x2c322fd4,0x1cb6af5a,0xae1f9fd9,0xae3faee9,0xaf02a814,0x2d272f91,0xacd8aff4,0x2ffc28d5,0xab05afa0,0xafedabb7,0x2e992515,0xad962aaa,0x2f5a2993,0x2e99a765,
0x2ff42ddc,0x2e1f2ed0,0x2e1f2fe6,0xa875afff,0xa8142c87,0xaffca9f1,0xadfe1648,0x2e5e2e99,0xaf5aaf30,0x2eb5a814,0xac5dafed,0xb000a934,0x2c32a8d5,0xa9932e3f,0x2f462875,0x2e7ca8d5,
0x2e991fd9,0x30002814,0x2f6e2ee9,0xac87af91,0x29932fa0,0xaed02875,0xacb02875,0x2f462d27,0xaff4ac32,0x2b5eaddc,0xad27afff,0xaff4a515,0x244ead96,0x1fd92fd4,0x2f3026a1,0x2e5ea9f1,
0x2814ad27,0x2dfeabb7,0x2ffc2d00,0xae5eae1f,0x2e992f80,0xaa4e2e7c,0xaa4e2c32,0x2fd42aaa,0xae7c1648,0x9cb6afdd,0xaddcafd4,0xafc91648,0xa875af91,0x2b5e2fbc,0x2f1a244e,0x2e3fab05,
0xab05aff4,0x244eafa0,0x2fbc28d5,0xaf91abb7,0x30002c32,0x26a12fff,0xa5db2ddc,0x30002515,0xaaaa2c5d,0xac32af6e,0xae7caf6e,0xaf8025db,0xad27afed,0x2e3f2dfe,0x2f021fd9,0x2e1fac07,
0xaf5aae5e,0xac5daf30,0x2eb59fd9,0xb000a44e,0x2e7ca30e,0x2ddc2e1f,0x1cb62f1a,0x2fc9a30e,0x217e2f46,0xaf02acb0,0xaf02aed0,0xaf1a2993,0xaf30ae99,0x2fbc29f1,0x2ee99648,0x2dfeac87,
0xafa0a515,0xafafa993,0x2d00aaaa,0xafa02765,0x2934ad96,0x2fed26a1,0x28142fd4,0x2f30a9f1,0x2c872fed,0xb0009fd9,0xaf6eadfe,0xae992c07,0xafffabb7,0x2fe6a17e,0x2ed0a17e,0x2ddcad00,
0xac322c87,0xaf462a4e,0x2993adba,0xae7c2c87,0xa875afed,0x2f1aab05,0x2b5e2ffc,0x2e3facd8,0x2f302e1f,0xaee92bb7,0xafbcad00,0xadfe2d27,0xaf6e9cb6,0x2eb5ac32,0x2eb5a515,0x2dbaad72,
0xaaaa2f5a,0xaed02e99,0xacb02e99,0x2f80ad96,0x2b5eaf30,0x2fafa44e,0x2d00ae5e,0xaf1a9fd9,0xac072f02,0xab05ad27,0xad4d2e1f,0x28142e3f,0x2c5daed0,0xa9f12fff,0x2d96addc,0x2c5dafe6,
0x28752f80,0xa8d52fe6,0xa8d52fc9,0x2e3faf46,0xa44eafd4,0x2f91adba,0x2b05af6e,0xafbc26a1,0x96482ffc,0xae99a44e,0xac872ee9,0x29f12d4d,0x2515aff8,0x1cb62f02,0x2d72ae3f,0x2c32aff8,
0x2eb52b05,0x2a4e2cd8,0x16482fed,0x2c5daffc,0xad72ad27,0x2cb0aff4,0x2765aff4,0xafff2b5e,0x2bb72e7c,0xaff82aaa,0xab5e2f80,0x2bb72c32,0xa814af6e,0x2b052c87,0x2d4dae99,0x2c07b000,
0x2feda8d5,0x2f30a30e,0x29342f02,0x2814afa0,0xafd49cb6,0x1648aed0,0x1648afe6,0xafdd2d72,0x2ed029f1,0xaf462eb5,0xa9932fdd,0x2cb029f1,0xad00ad4d,0x2e1f244e,0x2d27aee9,0x2bb7affc,
0x2d4daf02,0x2fbcae1f,0x2cd82d27,0x9fd9ae3f,0xaf5a2cb0,0xac87a993,0xa6a1af46,0xaf5a2ed0,0x2fffa5db,0xacb03000,0xa7653000,0x2d7226a1,0xaf1aa814,0x2fafa934,0x2d00af30,0x2b5eafed,
0x1648afbc,0x2c87affc,0x2e992934,0xa9f1ac07,0xac322faf,0xaf8028d5,0xaaaaae1f,0xae7c2faf,0x2f1aad72,0xa30e2ed0,0xa30e2fe6,0x2e1f1cb6,0xaffc26a1,0x2fedadba,0x2cd8af6e,0x2b05afd4,
0xad27ac32,0xa30ead72,0x2faf9cb6,0xad27a515,0x1fd92f6e,0xafbc2e99,0xacd8ac87,0xad4d3000,0x2c5dafbc,0x2a4e2b05,0x16482f91,0x2eb5a44e,0xaf802d00,0x2ed0afa0,0x2cb0afa0,0x2aaaafaf,
0xafe626a1,0xaddc1648,0x2fffaa4e,0xaed026a1,0x2d002c07,0xad272ffc,0xae1fa934,0xabb72fbc,0x1fd9afa0,0x2e5ea30e,0x244e2f02,0x2f30a8d5,0xadba2f46,0x2c87afe6,0x2c87afc9,0x2a4eaf80,
0xafff2d96,0xae7c2c5d,0xafc92c5d,0x2d72a9f1,0xa17e2dfe,0xaff42fbc,0xa8752ee9,0x2ff8af30,0x2fedad00,0xad4d2f1a,0x2f91ab5e,0x2e5eafaf,0x25dbae7c,0x16482993,0x29f1af46,0x25dbac32,
0xae3f2fff,0xaff82fc9,0xaff82e7c,0x2f02ad72,0x2c0725db,0xadfe2f5a,0x9fd92d96,0x2fedafdd,0x2f6eaf91,0xa6a12c07,0x2fd4acd8,0x2dbaaf30,0xa765ab5e,0x2aaaa30e,0x2993af02,0x2515ab5e,
0xa5db2dfe,0xad962ee9,0xaf5a2fbc,0x2fddaf30,0x2f46ab5e,0xa7652bb7,0x25152bb7,0x2f80aff8,0x2d00afc9,0x28d59cb6,0x2ff8addc,0x2d00ae7c,0xacd89648,0x2dfeac5d,0x2934aeb5,0x244eaa4e,
0x2c07217e,0x9fd92875,0xadfe2ff4,0x2fedaff8,0x2fddaf46,0x29f1a515,0x29f12765,0x2eb5af80,0x2515ad96,0x2ddcac87,0x2fffaeb5,0x2c32ad96,0xaf022b05,0x2fa0aee9,0x28d5ae5e,0x230ea934,
0x2f91ad00,0x2cd8ab5e,0xac072f1a,0x2f30afaf,0x2d96afc9,0x2eb5addc,0x2c879cb6,0x2d96ae7c,0xa993a6a1,0x2fc9af5a,0x2fe6af5a,0x2aaaac87,0xaff82e5e,0x2ff4affc,0x2875adfe,0x217ea814,
0x2f6eafed,0x2fd4af91,0xa6a12d4d,0x2dbaae5e,0x2515ad00,0x2fffaff8,0x2ddca8d5,0x2c32ad00,0xae1f2993,0x2fafafe6,0x2fafafc9,0x28d5aaaa,0xaf912fdd,0x2ee9af5a,0x2814ad96,0x1fd9a5db,
0x2b5eae7c,0x2f02af46,0x230e2993,0x2b5eac32,0xab059648,0x2e5eaeb5,0x2ee9ac5d,0x2934aa4e,0xafdd2e5e,0x2d96adfe,0x2f5aaffc,0x25dba814,0xaddc2faf,0x2cb0ad27,0x2765ad27,0x1cb6a30e,
0xa765a5db,0x2993a9f1,0x2aaa9648,0x2515a5db,0xaf022cd8,0x28d5a934,0x2fa0adfe,0x230ea44e,0xaf912ff8,0x2814a875,0x2ee9aff4,0x1fd9a17e,0xaa4e2ddc,0x26a1a765,0x26a1acb0,0x16489cb6,
0x2d722d96,0x25152c5d,0x2c322c5d,0x1cb6a9f1,0x2d272d4d,0xad00a814,0x2bb72c07,0x2e1f2b05,0x2cd82d00,0xaffcaf1a,0x2b052b5e,0x2fed2faf,0x2c872cb0,0xadbaaf80,0x2a4e2aaa,0x2c872ed0,
0x2e3f2ddc,0x2ff82ed0,0x2ff82fe6,0xaf02afff,0x2ee92e99,0x2d4d2f6e,0x2ffc3000,0xa44eac87,0x2f6e2f30,0xa6a12814,0x2fd42fed,0x2dba2934,0x2fc92fa0,0xaf46ad00,0x2f802faf,0x2fe62fa0,
0xac87ad4d,0x9648ac07,0x29f12814,0xae99ab05,0xa993ab5e,0x2ed02bb7,0x2cb02bb7,0xaf46aff8,0xa30ea765,0x2f1a2fff,0x2e1f2d72,0xa30eacb0,0x244e1648,0x1fd92c5d,0x2f302eb5,0x2e5e2a4e,
0xaee9ae1f,0xaffcaf02,0xad4dae3f,0x244e2d27,0xafddaf80,0xa9f1ae7c,0xa9f1ac32,0xaeb5aaaa,0xafe6b000,0x2d7225db,0x9cb6a6a1,0xaed0b000,0xaf02af91,0x2fa02fbc,0x28d5244e,0x230eab05,
0x2b052d00,0xa44e2b5e,0xafbcaf1a,0x2f912faf,0x16482765,0xafd4ad72,0xafddafff,0x16482cb0,0xaaaaa6a1,0xac32af5a,0xae7caf5a,0xaf80ac87,0xae1facd8,0x2d001fd9,0xabb7ad4d,0xad27afbc,
0x2f6e2e5e,0x2fd42f30,0xa6a11fd9,0x2dba244e,0x2fe62ff4,0x1cb62d27,0xad72ab5e,0x2ed02ff4,0x2e1f2f46,0xafafacb0,0xafafaed0,0xa8d52993,0x29342c87,0xac07af6e,0xafbcb000,0xaffcae99,
0xa8d5acb0,0x2875aaaa,0x2e3f2f80,0xa8d5aed0,0x29341648,0x2fed2eb5,0x28142c5d,0x2f302a4e,0x2e992cd8,0x16482d4d,0xa9f19fd9,0x2c872fbc,0x2fff2faf,0xafe6ad27,0xaed0ad27,0xaddca30e,
0xafc9ae99,0xaf80af5a,0x2f462d96,0xafe6ae99,0xaf02afed,0x28d5ab05,0x2fa02ffc,0x230eacd8,0xa934ad27,0x2fbc2f02,0x2c072e3f,0x2ffc2e1f,0x2a4e1cb6,0xa6a12c32,0xa6a12515,0x96482d72,
0xaaaa29f1,0xaed025db,0xacb025db,0x2f801648,0xaf1aaf91,0x2875ae5e,0xae3fafed,0xab5e2d4d,0x2c07a875,0x2b052ff8,0x2d4da17e,0xa814aff4,0x2eb52fc9,0xaf6ead72,0x2dba2fff,0x2eb52e7c,
0x2f022f80,0x2b5e2fe6,0x2b5e2fc9,0x230eaf46,0xacd826a1,0xaf30ad96,0xaf91a9f1,0x2c072fd4,0xad96affc,0x2fdd244e,0xa5dbaee9,0xaf5aad4d,0x2e7c217e,0xad722bb7,0x2fff2d00,0x2fc9217e,
0x2c5da934,0x2f5aa44e,0x30002cd8,0xaeb5adfe,0x2d722ff8,0xacb02d00,0xa7652d00,0x2fff28d5,0xaf02a515,0x217eaf80,0xaf1aaf46,0xaf022765,0xa814af5a,0x2b052fdd,0x2d4da5db,0x2c07ad96,
0xae5eafa0,0xa934aff4,0x2b05abb7,0xaee928d5,0x2eb51cb6,0x2d962ed0,0x2d962fe6,0x2c87ad72,0x27652f6e,0xaf80ac5d,0xaf46a5db,0xa5152f6e,0xaff4ad4d,0x2ff8244e,0xa17eaee9,0xa875affc,
0xad4d2875,0xafbc217e,0xacd8aff8,0x1fd92ff4,0xaa4eafe6,0x2e99aaaa,0x2fd42993,0xaa4eafc9,0x2fff2c87,0xacb02d96,0xa7652d96,0x2d722eb5,0xab5e2c07,0x2875af30,0xae3faf91,0xaf1aacd8,
0x2d962fbc,0x25db2ffc,0xafdda934,0x2f5a2c07,0xafc9a875,0xaaaaafa0,0x2993ad27,0xafe6a875,0x28d5ad72,0x2d002ed0,0x2d002fe6,0x2ff81cb6,0x2d4d2fd4,0xae5ead96,0xafeda9f1,0xaf9126a1,
0x2e1fa765,0x2ff49cb6,0xa8752ddc,0x2e1facb0,0x1fd92f5a,0xafbc25db,0xacd8afdd,0xad4d2d96,0xaeb5aee9,0x2f5aa934,0x30002b05,0x2c5dae5e,0x2f80230e,0xaed02b5e,0xacb02b5e,0xaaaa2f02,
0xacb0afd4,0x9cb6b000,0x2ddc2f5a,0xa765afd4,0x2ff42c07,0x217e2ffc,0xaff8a934,0x28752fbc,0xadfe28d5,0xa44eaff4,0x2cd8abb7,0xa934afa0,0x1648af46,0x25db2fe6,0x25db2fc9,0x29f12f80,
0xafff9648,0xae7ca6a1,0xafc9a6a1,0x2d722a4e,0x2ff81fd9,0x230e2ee9,0x2faf2814,0x217eaf91,0xafeda30e,0x2d4dafa0,0xaf91a8d5,0xae5e2f02,0x2fdd2515,0xb0002aaa,0x2f6e2993,0x2fdda765,
0xa30e2fff,0xad272fc9,0xad272e7c,0x2fafad72,0x2814afdd,0x2ffcaa4e,0x2dfeadba,0xae5ea5db,0xaa4e2f91,0xac5dac07,0xaeb52cd8,0x96482f30,0x2c32af1a,0xa9932ff4,0x2f46abb7,0x2e7caf1a,
0x2fdd1fd9,0x2dba2814,0x2a4e2ee9,0x25dbaf91,0xaf46a8d5,0x2765afaf,0xa515afaf,0xaf802e1f,0x2e3f2c32,0xafa02ddc,0xa17e2fff,0x2e3f2515,0xacd8adba,0x2dfe26a1,0x2934afd4,0x244eaf6e,
0x2814aff8,0x2dfeafaf,0x2ffca30e,0xae5ea17e,0xac872f46,0xaf5a2515,0xaf5aa765,0xa6a12f80,0x2e7cadba,0x1cb62e99,0x2ddc2c5d,0x2fc9adba,0xafaf2b05,0x2f1aaee9,0xab5eae5e,0xad00a934,
0xaf91a30e,0xacd8a8d5,0x2c07afa0,0xaf302f02,0x2dba2c32,0xac5d2fff,0xae992ddc,0x2dba2515,0xa993aeb5,0x2fc9a9f1,0x2fe6a9f1,0x2aaaafdd,0xa17e2fed,0xa30eadfe,0xafaf9fd9,0xaff82c07,
0xaa4e2fed,0xaeb52f91,0xac5dad4d,0x96482e5e,0x2e7cae3f,0x2ddc217e,0x1cb62fa0,0x2fc9ae3f,0xaff82993,0x2bb7afe6,0x2bb7afc9,0xab5eaaaa,0x2f3025db,0xafbc2a4e,0xaee92dba,0xadfe2fdd,
0x2f1a2515,0x2bb72993,0xaff42aaa,0x2f1aa765,0xab05adba,0x2e5eafd4,0x2ee926a1,0x2934af6e,0xa5db2fed,0xadba9fd9,0xaa4eadfe,0xafdd2c07,0x2ddcaf02,0xacb02ff8,0xa7652ff8,0x9cb62e3f,
0x2c32afdd,0x2f46af6e,0xa9933000,0x2e7cafdd,0xafaf2cd8,0xab5ea934,0x2f1aadfe,0xad00a44e,0x2f30217e,0xaee92faf,0xafbc230e,0xadfe2ff8,0xa9f1addc,0x2c5d2765,0x2c5d2cb0,0x2d961cb6,
0xa993aa4e,0x2765ac87,0xa515ac87,0xaaaa2dba,0xafa02f30,0xabb7244e,0xaff42e5e,0x28d51fd9,0x28142bb7,0xaf912e1f,0x1fd92d27,0x2ee9ad00,0x2fd4aed0,0xaf5a2fff,0x3000addc,0x2fd4afe6,
0xafaf2f46,0xafa02e7c,0xafa02c32,0x2d00a993,0x244e2c5d,0xaf913000,0xab052f5a,0x2fbcaeb5,0x3000adfe,0xac872e5e,0x2e99a814,0x2f6eaffc,0x2515ae1f,0x1cb62875,0x2d72aff4,0x2c32ae1f,
0x26a12b05,0xa9f12cd8,0xad962fed,0x2fd4affc,0x2fffae1f,0x2515230e,0x2c32230e,0x2ddcaf1a,0x2875ae7c,0x2d27aaaa,0x2fa0af80,0x2875ac32,0xaee929f1,0x2f91ae99,0x9fd9ac87,0xa8149648,
0x2fedaf1a,0x2f30ae3f,0x29342875,0x2814ab5e,0x26a1addc,0x3000afc9,0x3000ae7c,0xa5db9cb6,0xaed02a4e,0x2f46afd4,0x2993ae99,0xacb02a4e,0xae3f2ffc,0x2d27ae5e,0xae1f2814,0xaf022dfe,
0x9fd9abb7,0x2c07ad27,0x2fedae1f,0xadfe2d00,0xaf6e2cb0,0x25dba993,0x2c5daf46,0xaf6e2ed0,0xaddc2fdd,0xa5159648,0xac329648,0xafff2fd4,0x28d52814,0xabb72934,0xaff42f30,0xafa02fed,
0xb0002ee9,0xae992dfe,0x2c87af30,0xaf6e2fbc,0xac322f02,0xaf802f1a,0xaaaaa17e,0xae7c2f02,0x2b5e1cb6,0xaff42fc9,0xaff42e7c,0xad272ddc,0x2ffcaeb5,0xafed3000,0xacd82f5a,0xab052c5d,
0xa17e2c32,0xad002d72,0xabb71cb6,0xa17e2515,0x2dfea9f1,0xac072c87,0xafed2e99,0x1fd91648,0x2fd4afbc,0xa9f12b05,0xad962f91,0x26a1a44e,0x2aaaae3f,0xa76528d5,0x251528d5,0x2993a875,
0x2fe6aeb5,0x2ddcadba,0xafff2f6e,0x2ed0aeb5,0x2e3fafbc,0x2e1fadfe,0xad272f30,0x2f02aee9,0x1fd9ab5e,0x2e5eae3f,0x244e2875,0x2f30af1a,0xad962993,0x2e99ae7c,0x2e99ac32,0x2f5aaf46,
0x299329f1,0xa76525db,0x251525db,0x2aaa1648,0x28d52934,0xaf02acd8,0x230e244e,0x2fa02dfe,0x28142875,0xaf91aff8,0x1fd9217e,0x2ee92ff4,0x26a12765,0xaa4eaddc,0x16481cb6,0x26a12cb0,
0x2f022f46,0x2b5e2e7c,0x2b5e2c32,0x230ea993,0x2e5e2eb5,0xab051648,0x29342a4e,0x2ee92c5d,0x2d962dfe,0xafddae5e,0x25db2814,0x2f5a2ffc,0x2cb02d27,0xaddcafaf,0x1cb6230e,0x27652d27,
0x2fd42f91,0x2f6e2fed,0x2dba2e5e,0xa6a1ad4d,0x2fff2ff8,0x25152d00,0x2c322d00,0x2ddc28d5,0x2faf2fe6,0xae1fa993,0x28d52aaa,0x2faf2fc9,0x2ee92f5a,0xaf91afdd,0x1fd925db,0x28142d96,
0x2cd82b5e,0x2f912d00,0x2f302faf,0xac07af1a,0x2eb52ddc,0x2d962fc9,0x2d962e7c,0x2c871cb6,0x2fc92f5a,0xa99326a1,0x2aaa2c87,0x2fe62f5a,0x2ff42ffc,0xaff8ae5e,0x217e2814,0x28752dfe,
0x9fd9a875,0x2c07a17e,0x2fed2ff8,0xadfeaff4,0x29f12515,0x2fdd2f46,0x2eb52f80,0x29f1a765,0x2ddc2c87,0x25152d96,0x2c322d96,0x2fff2eb5,0x2fa02ee9,0xaf02ab05,0x230e2934,0x28d52e5e,
0xad96aee9,0xa5dbadfe,0x2fdd2f30,0xaf5aafbc,0xa765abb7,0x2f462b5e,0x2f802ff8,0x2515abb7,0x28d51cb6,0x2d002fc9,0x2d002e7c,0x2ff82ddc,0x2dfe2c5d,0xacd81648,0x244e2a4e,0x29342eb5,
0xaff8afc9,0xae3fafff,0x2f022d72,0xaff8ae7c,0xadfeaf5a,0x2c07a5db,0x2fed2fdd,0x9fd9ad96,0xa6a1ac07,0x2f6e2f91,0x2dba2f30,0x2fd42cd8,0x2aaa230e,0xa7652b5e,0x25152b5e,0x29932f02,
0xae7cac5d,0xafffad96,0x2d7229f1,0xafc9ac5d,0xaff4afbc,0xa17eadfe,0x2ff82f30,0xa875aee9,0xad4daf1a,0x2fed2d00,0x2e5e2faf,0x2f912b5e,0x1648a993,0x25db2e7c,0x25db2c32,0x29f12f46,
0xaddc9648,0xafe6a6a1,0xaed0a6a1,0x2fff2a4e,0xad27affc,0x2d00ac07,0xabb7afbc,0xae1f2934,0x2e5e230e,0x1fd92fa0,0x2f3028d5,0x244eaf02,0x2c872fe6,0xadbaaf46,0x2a4e2f80,0x2c872fc9,
0xa30e2d72,0xad272c32,0xad272515,0x2faf1cb6,0xafbcae99,0x1fd9af6e,0xad4db000,0xacd82c87,0x2a4eab05,0x2c5d2fbc,0x2eb5244e,0x1648af91,0x2ed02fa0,0xaf80ad00,0x2aaa2faf,0x2cb02fa0,
0x2c872ffc,0x16482fbc,0xa9f12c07,0x2e99a934,0xaf80a8d5,0xac32afaf,0xae7cafaf,0xaaaa2e1f,0xa30eaed0,0x2f1a2d72,0x2e1f9cb6,0xa30eafe6,0x2fed2dba,0xaffca6a1,0x2b052fd4,0x2cd82f6e,
0x2fbc2e1f,0x2d4d2f02,0x9fd92e3f,0x2cd8ad27,0xac872993,0xaf5aacb0,0xaf5aaed0,0xa6a12f46,0xacb0b000,0x2fff25db,0x2d72a6a1,0xa765b000,0x2faf2934,0xaf1a2814,0x2b5e2fed,0x2d002f30,
0x2f30230e,0x2fed28d5,0x28142fa0,0x2934af02,0x16482ed0,0xafd41cb6,0xafddad72,0x16482fe6,0xaf46aeb5,0x2ed0a9f1,0x2cb0a9f1,0xa993afdd,0x2e1fa44e,0xad002d4d,0x2bb72ffc,0x2d272ee9,
0x2a4eacd8,0x2eb5ab05,0x2c5d2ffc,0x1648afed,0x2cb02ff4,0xad722d27,0xafffab5e,0x27652ff4,0xaff8aaaa,0x2bb7ae7c,0x2bb7ac32,0xab5eaf80,0x2b05ac87,0xa8142f6e,0x2c073000,0x2d4d2e99,
0xa8d5afe6,0x2875af80,0x2e3f2f46,0xa8d5afc9,0x2f912dba,0xa44e2fd4,0xafbca6a1,0x2b052f6e,0xae99244e,0x9648affc,0x29f1ad4d,0xac87aee9,0x1cb6af02,0x25152ff8,0x2c322ff8,0x2d722e3f,
0xaed0ae99,0xaaaaaf5a,0x2f802d96,0xacb0ae99,0x2faf244e,0x2b5e2f30,0xaf1a1fd9,0x2d002e5e,0xab052d27,0xac07af02,0x2814ae3f,0xad4dae1f,0xa9f1afff,0x2c5d2ed0,0x2c5d2fe6,0x2d962ddc,
0xaf46aa4e,0xac32ac87,0xae7cac87,0x29932dba,0x2f1a2b05,0xa8752fed,0x2e3f2cd8,0x2b5eaffc,0xaee9abb7,0x2f30ae1f,0xadfead27,0xafbc2d00,0x2eb52c32,0xaf6e1cb6,0x2dba2d72,0x2eb52515,
0xafaf2993,0xafa02515,0xafa0a765,0x2d002aaa,0x2feda6a1,0x29342d96,0x2f3029f1,0x2814afd4,0xb0001fd9,0x2c87afed,0xae99ac07,0xaf6e2dfe,0x2fe6217e,0xafff2bb7,0x2ddc2d00,0x2ed0217e,
0xac5d2f30,0xaf5a2e5e,0xb000244e,0x2eb51fd9,0x2ddcae1f,0x2e7c230e,0x2fc9230e,0x1cb6af1a,0xaf022cb0,0x217eaf46,0xaf1aa993,0xaf022ed0,0x2fbca9f1,0xaf302e99,0x2dfe2c87,0x2ee91648,
0x244e2fa0,0xab052ff4,0xaf912bb7,0x2fbca8d5,0x26a1afff,0x3000ac32,0x3000a515,0xa5dbaddc,0xac322f6e,0xaaaaac5d,0xaf80a5db,0xae7c2f6e,0x2e3fadfe,0xad272fed,0x2e1f2c07,0x2f029fd9,
0x2dfe2bb7,0x28142d27,0xae5e2e1f,0x2ffcad00,0xaa4eae7c,0x2e99af80,0x2fd4aaaa,0xaa4eac32,0x9cb62fdd,0xae7c9648,0xafc99648,0xaddc2fd4,0x2b5eafbc,0xa8752f91,0x2e3f2b05,0x2f1aa44e,
0x3000a814,0x2e999fd9,0xac872f91,0x2f6eaee9,0xaed0a875,0x2993afa0,0x2f46ad27,0xacb0a875,0x2b5e2ddc,0xaff42c32,0xaff42515,0xad272fff,0x1fd9afd4,0x244e2d96,0x2e5e29f1,0x2f30a6a1,
0x2e1faed0,0x2ff4addc,0xa8752fff,0x2e1fafe6,0xaffc29f1,0xa814ac87,0x2e5eae99,0xadfe9648,0x2eb52814,0xaf5a2f30,0xb0002934,0xac5d2fed,0xa993ae3f,0x2c3228d5,0x2e7c28d5,0x2f46a875,
0x2515afd4,0x2d72b000,0x1cb62f5a,0x2c32afd4,0xae3f2ee9,0xae1f1fd9,0x2d27af91,0xaf022814,0x2ffca8d5,0xacd82ff4,0xafed2bb7,0xab052fa0,0xad96aaaa,0x2e99a515,0x2e992765,0x2f5aa993,
0x1cb6adba,0x2cb0aeb5,0x2765aeb5,0xaddc2f6e,0xaff82d4d,0xa30ea814,0xafaf2c07,0xa17e2b05,0xa44e2e3f,0xadfe2b5e,0xa9342f1a,0x2cd8a875,0x2fddacb0,0xb0002f80,0x2f6eaaaa,0x2fddaed0,
0xad009cb6,0xa17ea765,0xa17eacb0,0xabb72ddc,0xaee92fdd,0xad4d2a4e,0xaffc2dba,0x244e25db,0x29f12934,0xafd42ee9,0xa6a12e5e,0x2d96ab05,0x2fc9af1a,0xaf462ff4,0x2f80abb7,0x2fe6af1a,
0xafdd2d4d,0xadba2c07,0xaa4ea814,0xa5db2b05,0xaaaa2f1a,0xafc92f02,0xafe62f02,0x2993a17e,0x2e3fa765,0xafa02fff,0xa17e2d72,0x2e3facb0,0x2e5eb000,0xad4d2eb5,0x2f91ac5d,0x2fedaf5a,
0xaee92ff8,0xaffc2faf,0xad4d230e,0x244e217e,0x25db2aaa,0xaf6e2fe6,0xaf6e2fc9,0x2c5da993,0x2fe6adba,0xad722e99,0x1cb62c5d,0x2ed0adba,0x2bb7af30,0xa8d52c07,0x2fa0acd8,0x2ff4af91,
0xa9342e3f,0xae5e2f1a,0xaee92b5e,0x2b05a875,0x2dbaa765,0xac5d2d72,0xae992fff,0x2dbaacb0,0x2f80afd4,0xa7652a4e,0x25152a4e,0x2f46ae99,0x217eacd8,0x230e1fd9,0x2fafad4d,0x2ff8afbc,
0x29f1244e,0xa6a12934,0xafd42dfe,0x2d96acd8,0x2fe6ae3f,0x1cb6217e,0xad722fa0,0x2ed0ae3f,0x2d27af80,0x2875a515,0x28752765,0x2fa0af46,0xa934a5db,0x2c07aa4e,0x2fbcadba,0x2ffcafdd,
0x2f1aacb0,0x2bb7aaaa,0xaff42f80,0x2f1aaed0,0x2f30b000,0x2cd8ac5d,0xac072eb5,0x2f91af5a,0x25dbacd8,0x2dbaad4d,0x2a4e1fd9,0x2fddafbc,0xad722875,0x2e7cae1f,0x2fc9ae1f,0x2fffaff4,
0x2fc9afdd,0x2f80af6e,0xaf463000,0x2fe6afdd,0x2bb7ae5e,0x2fa0af91,0xa8d52d4d,0x2ff4afed,0xa934a17e,0x2fbcafaf,0x2c07a30e,0x2ffcaff8,0xaf5a2d72,0x2fd4afc9,0x2fd4ae7c,0x3000afff,
0x9d4d9e16,0xada6ae7d,0x9b769c84,0xabf0accf,0x985299e4,0xa897aa43,0x90b6957f,0xa102a5d8,0x13db0a48,0x242c1aad,0x191b1712,0x296d2783,0x1c201aad,0x2c632b1a,0x1db21ce9,0x2e112d3a,
0xa3f4a491,0xae51af42,0xa199a2c6,0xac70ad60,0x9e7ba06b,0xa922ab00,0x97129c20,0xa199a688,0x19e410b6,0x24aa1b76,0x1fa81d4d,0x2a112833,0x222f2102,0x2ce82bf0,0x2445235d,0x2ec92dd8,
0xa6a1a79c,0xaefcb004,0xa4aaa5a5,0xace8adf2,0xa166a35d,0xa9acabbe,0x99e49edf,0xa22fa738,0x1ce913db,0x25281c20,0x2262206b,0x2ab528a4,0x2528242c,0x2d6d2c63,0x271f2623,0x2f822e77,
0xa8a4a954,0xafa8b067,0xa688a7e8,0xad60ae84,0xa38fa528,0xaa37ac3d,0x9c20a0d0,0xa2c6a7e8,0x1edf157f,0x25a51c84,0x2478222f,0x2b592915,0x273825d8,0x2df22ccf,0x28fc284c,0x301d2f16,
0xa9f8aadb,0xb02ab0ca,0xa833a915,0xadd8af16,0xa4dca6a1,0xaac1ac9c,0x9d4da22f,0xa35da84c,0x206b1712,0x26231ce9,0x25bf23f4,0x2bfd2987,0x28a42783,0x2e772d3a,0x2a692987,0x307a2fb5,
0xab4cac31,0xb081b12e,0xa922aa37,0xae51afa8,0xa5f1a80d,0xab4cacfb,0x9e7ba38f,0xa3f4a8a4,0x21661852,0x26a11d4d,0x270524dc,0x2c5029f8,0x29ac2897,0x2efc2da6,0x2bd72ac1,0x30d7302a,
0xac50acf5,0xb0d7b192,0xaa11ab59,0xaec9b01d,0xa705a8ca,0xabd7ad5a,0x9fa8a478,0xa445a8fc,0x2262191b,0x271f1db2,0x282625bf,0x2ca22a69,0x2ab5296d,0x2f822e11,0x2ca22bfd,0x3135307a,
0xacfbadb9,0xb12eb1f7,0xab00ac3d,0xaf42b067,0xa80da987,0xac31adb9,0xa06ba528,0xa491a954,0x235d19e4,0x279c1e16,0x28ca26a1,0x2cf52adb,0x2bbe2a43,0x30042e7d,0x2d5a2c9c,0x319230ca,
0xb185b25c,0xb426b4cc,0xafbbb0b1,0xb1c6b306,0xac76ae18,0xaea3b08a,0xa4dca9ac,0xa738ac37,0x280d1e7b,0x2a0520d0,0x2d472b4c,0x2fdb2d6d,0x30472ee9,0x32663128,0x31f0311b,0x347933a8,
0xb1ddb2c1,0xb453b501,0xb01ab0fb,0xb204b352,0xacbcae77,0xaee9b0ba,0xa528aa05,0xa783ac63,0x284c1edf,0x2a432102,0x2d992bbe,0x30172da6,0x308a2f55,0x32aa315f,0x324f316b,0x34aa33fc,
0xb235b327,0xb481b537,0xb057b145,0xb242b39e,0xad01aed6,0xaf2fb0eb,0xa573aa5d,0xa7cfac90,0x288b1f44,0x2a822134,0x2deb2c18,0x30412ddf,0x30ce2fc2,0x32ef3196,0x32ae31bc,0x34db3428,
0xb28db38e,0xb4afb56d,0xb094b18f,0xb280b3eb,0xad47af36,0xaf75b11b,0xa5bfaab5,0xa80dacbc,0x28ca1fa8,0x2ac12166,0x2e3e2c50,0x306a2e18,0x31113017,0x333531cd,0x330d320e,0x350d3452,
0xb2e5b3f5,0xb4ddb5a3,0xb0d1b1da,0xb2beb41c,0xad8caf95,0xafbbb14b,0xa60aab0d,0xa833ace8,0x29092006,0x2b002199,0x2e902c89,0x30942e51,0x3155304d,0x337a3204,0x336d325f,0x3540347c,
0xb33eb42e,0xb50cb5da,0xb10eb224,0xb2fcb443,0xadd2aff5,0xb001b17c,0xa655ab65,0xa859ad14,0x29482039,0x2b4021cb,0x2ee32cc2,0x30be2e8a,0x31993084,0x33c0323b,0x33cd32b1,0x357234a6,
0xb398b463,0xb53ab612,0xb14bb26f,0xb33bb469,0xae18b02a,0xb024b1ac,0xa6a1abbe,0xa87ead40,0x2987206b,0x2b7f21fd,0x2f362cfb,0x30e72ec3,0x31dd30ba,0x34033273,0x34173303,0x35a534d1,
0xb3f2b497,0xb569b64a,0xb189b2bb,0xb37ab490,0xae5eb05a,0xb047b1dd,0xa6ecac0b,0xa8a4ad6d,0x29c6209d,0x2bbe222f,0x2f882d34,0x31112efc,0x322130f1,0x342632aa,0x34483356,0x35d934fc,
0xb599b682,0xb722b82e,0xb3b9b4b7,0xb4ddb5f9,0xb06ab20e,0xb185b398,0xa8caad99,0xa9f8aefc,0x2bfd2262,0x2cfb23f4,0x313b2f36,0x328d3081,0x344932e2,0x35693453,0x360d3527,0x37bd368b,
0xb5c9b6bb,0xb755b84d,0xb3f8b4df,0xb4feb622,0xb08db23e,0xb1a9b3ca,0xa8f0adc5,0xaa1eaf29,0x2c1e2294,0x2d1b2413,0x31652f6f,0x32b7309d,0x346d331a,0x358e3470,0x36413553,0x37f536ba,
0xb5f9b6f5,0xb789b86d,0xb41cb506,0xb51fb64c,0xb0b1b26f,0xb1cdb3fc,0xa915adf2,0xaa43af55,0x2c3d22c6,0x2d3a242c,0x318f2fa8,0x32e230ba,0x34903352,0x35b3348d,0x3676357e,0x381736e8,
0xb629b72f,0xb7bdb88d,0xb43cb52e,0xb540b676,0xb0d4b2a1,0xb1f0b417,0xa93bae1e,0xaa69af82,0x2c5d22f9,0x2d5a2445,0x31b92fe2,0x330d30d7,0x34b4338b,0x35d934aa,0x36ab35ab,0x38343717,
0xb65ab76a,0xb7f1b8ad,0xb45cb556,0xb561b6a0,0xb0f7b2d2,0xb214b430,0xa961ae4b,0xaa8fafaf,0x2c7d232b,0x2d79245f,0x31e3300e,0x333830f4,0x34d833c3,0x35fe34c7,0x36e035d7,0x38513746,
0xb68bb7a5,0xb813b8ce,0xb47cb57e,0xb582b6ca,0xb11bb303,0xb238b449,0xa987ae77,0xaab5afdb,0x2c9c235d,0x2d992478,0x320e302a,0x33633111,0x34fc33fc,0x362434e4,0x37173604,0x386f3775,
0xb6bdb7e2,0xb82eb8f0,0xb49cb5a7,0xb5a3b6f5,0xb13eb335,0xb25cb463,0xa9acaea3,0xaadbb004,0x2cbc238f,0x2db92491,0x32383047,0x338e312e,0x3520341a,0x364a3501,0x374d3631,0x388d37a5,
0xb6efb80f,0xb849b911,0xb4bdb5d0,0xb5c5b720,0xb162b366,0xb280b47c,0xa9d2aed0,0xab00b01a,0x2cdb23c2,0x2dd824aa,0x32623064,0x33b9314b,0x35453437,0x3670351f,0x3785365e,0x38ab37d6,
0xb865b934,0xb94dba5c,0xb5e7b74c,0xb6fcb85a,0xb2a4b495,0xb3c6b564,0xab26b031,0xac2bb0e4,0x2df824c3,0x2ef6258c,0x33e43168,0x34a13252,0x3697353c,0x37d4362d,0x38ca3803,0x39d038d0,
0xb880b957,0xb96bba84,0xb609b777,0xb720b872,0xb2c8b4af,0xb3ebb57e,0xab4cb047,0xac3db0fb,0x2e1824dc,0x2f1625a5,0x34083185,0x34b7326f,0x36bd355a,0x37fd364c,0x38e9381c,0x39f338eb,
0xb89cb97a,0xb98abaad,0xb62bb7a4,0xb744b88a,0xb2ecb4c9,0xb408b599,0xab72b05d,0xac50b111,0x2e3724f5,0x2f3625bf,0x341e31a2,0x34ce328d,0x36e43577,0x3813366b,0x39093835,0x3a173906,
0xb8b9b99e,0xb9aabad7,0xb64db7d0,0xb768b8a2,0xb310b4e2,0xb41ab5b3,0xab98b074,0xac63b128,0x2e57250f,0x2f5525d8,0x343331c0,0x34e432aa,0x370b3595,0x3828368a,0x3929384e,0x3a3b3922,
0xb8d6b9c3,0xb9cabb02,0xb670b7fd,0xb78cb8ba,0xb335b4fc,0xb42db5ce,0xabbeb08a,0xac76b13e,0x2e772528,0x2f7525f1,0x344931dd,0x34fa32c8,0x373335b3,0x383d36a9,0x39493868,0x3a60393e,
0xb8f3b9e8,0xb9ebbb2d,0xb693b815,0xb7b1b8d2,0xb359b516,0xb43fb5e9,0xabe3b0a1,0xac89b155,0x2e972541,0x2f95260a,0x345f31fa,0x351132e5,0x375b35d2,0x385236c8,0x396a3881,0x3a86395a,
0xb910ba0e,0xba0cbb59,0xb6b6b82c,0xb7d6b8eb,0xb37db530,0xb452b604,0xac05b0b7,0xac9cb16b,0x2eb6255a,0x2fb52623,0x34753217,0x35273303,0x378335f0,0x386836e8,0x398c389b,0x3aac3977,
0xb92eba35,0xba2dbb87,0xb6d9b843,0xb7fbb904,0xb3a2b54a,0xb464b61e,0xac18b0ce,0xacafb182,0x2ed62573,0x2fd5263c,0x348b3235,0x353e3321,0x37ab360e,0x387d3708,0x39ae38b6,0x3ad33994,
0x9ce99db2,0xad3aae11,0x9aad9c20,0xab1aac63,0x9712991b,0xa783a96d,0x8a4893db,0x9aada42c,0x157f10b6,0x25d82102,0x19e41852,0x2a432897,0x1c841b76,0x2ccf2bf0,0x1e161d4d,0x2e7d2da6,
0xa35da445,0xadd8aec9,0xa102a22f,0xabf0ace8,0x9d4d9fa8,0xa833aa11,0x90b699e4,0x9b76a4aa,0x1c201712,0x26882199,0x206b1e7b,0x2b002922,0x22c62199,0x2d602c70,0x249123f4,0x2f422e51,
0xa623a71f,0xae77af82,0xa42ca528,0xac63ad6d,0xa06ba262,0xa8a4aab5,0x93db9ce9,0x9c20a528,0x1edf19e4,0x2738222f,0x235d2166,0x2bbe29ac,0x25a524aa,0x2df22ce8,0x279c26a1,0x30042efc,
0xa84ca8fc,0xaf16b01d,0xa5d8a738,0xaccfadf2,0xa22fa478,0xa915ab59,0x957f9edf,0x9c84a5a5,0x20d01c20,0x27e822c6,0x2528238f,0x2c3d2a37,0x27e82688,0x2e842d60,0x295428a4,0x30672fa8,
0xa987aa69,0xafb5b07a,0xa783a8a4,0xad3aae77,0xa3f4a5bf,0xa987abfd,0x9712a06b,0x9ce9a623,0x222f1d4d,0x284c235d,0x26a124dc,0x2c9c2ac1,0x29152833,0x2f162dd8,0x2adb29f8,0x30ca302a,
0xaac1abd7,0xb02ab0d7,0xa897a9ac,0xada6aefc,0xa4dca705,0xa9f8ac50,0x9852a166,0x9d4da6a1,0x238f1e7b,0x28a423f4,0x280d25f1,0x2cfb2b4c,0x2a372922,0x2fa82e51,0x2c312b4c,0x312e3081,
0xabfdaca2,0xb07ab135,0xa96daab5,0xae11af82,0xa5bfa826,0xaa69aca2,0x991ba262,0x9db2a71f,0x24781fa8,0x28fc2445,0x28ca2705,0x2d5a2bd7,0x2b592a11,0x301d2ec9,0x2cf52c50,0x319230d7,
0xac9cad5a,0xb0cab192,0xaa43abbe,0xae7db004,0xa6a1a8ca,0xaadbacf5,0x99e4a35d,0x9e16a79c,0x2528206b,0x29542491,0x2987280d,0x2db92c31,0x2c3d2b00,0x30672f42,0x2db92cfb,0x31f7312e,
0xb11bb1f0,0xb3a8b479,0xaee9b047,0xb128b266,0xab4cad47,0xad6dafdb,0x9e7ba80d,0xa0d0aa05,0x29ac24dc,0x2c372738,0x2e182c76,0x308a2ea3,0x30b12fbb,0x330631c6,0x325c3185,0x34cc3426,
0xb16bb24f,0xb3fcb4aa,0xaf55b08a,0xb15fb2aa,0xabbead99,0xada6b017,0x9edfa84c,0xa102aa43,0x2a052528,0x2c632783,0x2e772cbc,0x30ba2ee9,0x30fb301a,0x33523204,0x32c131dd,0x35013453,
0xb1bcb2ae,0xb428b4db,0xafc2b0ce,0xb196b2ef,0xac18adeb,0xaddfb041,0x9f44a88b,0xa134aa82,0x2a5d2573,0x2c9027cf,0x2ed62d01,0x30eb2f2f,0x31453057,0x339e3242,0x33273235,0x35373481,
0xb20eb30d,0xb452b50d,0xb017b111,0xb1cdb335,0xac50ae3e,0xae18b06a,0x9fa8a8ca,0xa166aac1,0x2ab525bf,0x2cbc280d,0x2f362d47,0x311b2f75,0x318f3094,0x33eb3280,0x338e328d,0x356d34af,
0xb25fb36d,0xb47cb540,0xb04db155,0xb204b37a,0xac89ae90,0xae51b094,0xa006a909,0xa199ab00,0x2b0d260a,0x2ce82833,0x2f952d8c,0x314b2fbb,0x31da30d1,0x341c32be,0x33f532e5,0x35a334dd,
0xb2b1b3cd,0xb4a6b572,0xb084b199,0xb23bb3c0,0xacc2aee3,0xae8ab0be,0xa039a948,0xa1cbab40,0x2b652655,0x2d142859,0x2ff52dd2,0x317c3001,0x3224310e,0x344332fc,0x342e333e,0x35da350c,
0xb303b417,0xb4d1b5a5,0xb0bab1dd,0xb273b403,0xacfbaf36,0xaec3b0e7,0xa06ba987,0xa1fdab7f,0x2bbe26a1,0x2d40287e,0x302a2e18,0x31ac3024,0x326f314b,0x3469333b,0x34633398,0x3612353a,
0xb356b448,0xb4fcb5d9,0xb0f1b221,0xb2aab426,0xad34af88,0xaefcb111,0xa09da9c6,0xa22fabbe,0x2c0b26ec,0x2d6d28a4,0x305a2e5e,0x31dd3047,0x32bb3189,0x3490337a,0x349733f2,0x364a3569,
0xb527b60d,0xb68bb7bd,0xb2e2b449,0xb453b569,0xaf36b13b,0xb081b28d,0xa262abfd,0xa3f4acfb,0x2d9928ca,0x2efc29f8,0x320e306a,0x33983185,0x34b733b9,0x35f934dd,0x36823599,0x382e3722,
0xb553b641,0xb6bab7f5,0xb31ab46d,0xb470b58e,0xaf6fb165,0xb09db2b7,0xa294ac1e,0xa413ad1b,0x2dc528f0,0x2f292a1e,0x323e308d,0x33ca31a9,0x34df33f8,0x362234fe,0x36bb35c9,0x384d3755,
0xb57eb676,0xb6e8b817,0xb352b490,0xb48db5b3,0xafa8b18f,0xb0bab2e2,0xa2c6ac3d,0xa42cad3a,0x2df22915,0x2f552a43,0x326f30b1,0x33fc31cd,0x3506341c,0x364c351f,0x36f535f9,0x386d3789,
0xb5abb6ab,0xb717b834,0xb38bb4b4,0xb4aab5d9,0xafe2b1b9,0xb0d7b30d,0xa2f9ac5d,0xa445ad5a,0x2e1e293b,0x2f822a69,0x32a130d4,0x341731f0,0x352e343c,0x36763540,0x372f3629,0x388d37bd,
0xb5d7b6e0,0xb746b851,0xb3c3b4d8,0xb4c7b5fe,0xb00eb1e3,0xb0f4b338,0xa32bac7d,0xa45fad79,0x2e4b2961,0x2faf2a8f,0x32d230f7,0x34303214,0x3556345c,0x36a03561,0x376a365a,0x38ad37f1,
0xb604b717,0xb775b86f,0xb3fcb4fc,0xb4e4b624,0xb02ab20e,0xb111b363,0xa35dac9c,0xa478ad99,0x2e772987,0x2fdb2ab5,0x3303311b,0x34493238,0x357e347c,0x36ca3582,0x37a5368b,0x38ce3813,
0xb631b74d,0xb7a5b88d,0xb41ab520,0xb501b64a,0xb047b238,0xb12eb38e,0xa38facbc,0xa491adb9,0x2ea329ac,0x30042adb,0x3335313e,0x3463325c,0x35a7349c,0x36f535a3,0x37e236bd,0x38f0382e,
0xb65eb785,0xb7d6b8ab,0xb437b545,0xb51fb670,0xb064b262,0xb14bb3b9,0xa3c2acdb,0xa4aaadd8,0x2ed029d2,0x301a2b00,0x33663162,0x347c3280,0x35d034bd,0x372035c5,0x380f36ef,0x39113849,
0xb803b8ca,0xb8d0b9d0,0xb53cb697,0xb62db7d4,0xb168b3e4,0xb252b4a1,0xa4c3adf8,0xa58caef6,0x30312b26,0x30e42c2b,0x349532a4,0x356433c6,0x374c35e7,0x385a36fc,0x39343865,0x3a5c394d,
0xb81cb8e9,0xb8ebb9f3,0xb55ab6bd,0xb64cb7fd,0xb185b408,0xb26fb4b7,0xa4dcae18,0xa5a5af16,0x30472b4c,0x30fb2c3d,0x34af32c8,0x357e33eb,0x37773609,0x38723720,0x39573880,0x3a84396b,
0xb835b909,0xb906ba17,0xb577b6e4,0xb66bb813,0xb1a2b41e,0xb28db4ce,0xa4f5ae37,0xa5bfaf36,0x305d2b72,0x31112c50,0x34c932ec,0x35993408,0x37a4362b,0x388a3744,0x397a389c,0x3aad398a,
0xb84eb929,0xb922ba3b,0xb595b70b,0xb68ab828,0xb1c0b433,0xb2aab4e4,0xa50fae57,0xa5d8af55,0x30742b98,0x31282c63,0x34e23310,0x35b3341a,0x37d0364d,0x38a23768,0x399e38b9,0x3ad739aa,
0xb868b949,0xb93eba60,0xb5b3b733,0xb6a9b83d,0xb1ddb449,0xb2c8b4fa,0xa528ae77,0xa5f1af75,0x308a2bbe,0x313e2c76,0x34fc3335,0x35ce342d,0x37fd3670,0x38ba378c,0x39c338d6,0x3b0239ca,
0xb881b96a,0xb95aba86,0xb5d2b75b,0xb6c8b852,0xb1fab45f,0xb2e5b511,0xa541ae97,0xa60aaf95,0x30a12be3,0x31552c89,0x35163359,0x35e9343f,0x38153693,0x38d237b1,0x39e838f3,0x3b2d39eb,
0xb89bb98c,0xb977baac,0xb5f0b783,0xb6e8b868,0xb217b475,0xb303b527,0xa55aaeb6,0xa623afb5,0x30b72c05,0x316b2c9c,0x3530337d,0x36043452,0x382c36b6,0x38eb37d6,0x3a0e3910,0x3b593a0c,
0xb8b6b9ae,0xb994bad3,0xb60eb7ab,0xb708b87d,0xb235b48b,0xb321b53e,0xa573aed6,0xa63cafd5,0x30ce2c18,0x31822caf,0x354a33a2,0x361e3464,0x384336d9,0x390437fb,0x3a35392e,0x3b873a2d,
0x214d2216,0x319b326c,0x1f762084,0x2fe830c8,0x1c521de4,0x2c962e40,0x14b6197f,0x250229d7,0x97db8e48,0xa82c9ead,0x9d1b9b12,0xad6bab82,0xa0209ead,0xb05eaf14,0xa1b2a0e9,0xb204b131,
0x27f32890,0x3241332b,0x259826c6,0x306a3156,0x227b246b,0x2d202efb,0x1b122020,0x25982a87,0x9de494b6,0xa8aa9f76,0xa3a8a14d,0xae0eac32,0xa62fa502,0xb0e1afe8,0xa845a75d,0xb2b6b1cc,
0x2aa02b9b,0x32e733e8,0x28aa29a5,0x30e131e5,0x2566275d,0x2daa2fb6,0x1de422df,0x262f2b36,0xa0e997db,0xa927a020,0xa661a46b,0xaeb0aca2,0xa927a82c,0xb163b05e,0xab1daa22,0xb368b266,
0x2ca22d52,0x338d3452,0x2a872be6,0x31563273,0x278f2927,0x2e333039,0x202024cf,0x26c62be6,0xa2df997f,0xa9a5a084,0xa877a62f,0xaf53ad13,0xab36a9d7,0xb1e5b0c8,0xacfaac4b,0xb40cb300,
0x2df52ed6,0x341834b0,0x2c322d13,0x31cc3300,0x28dc2aa0,0x2ebd3096,0x214d262f,0x275d2c4b,0xa46b9b12,0xaa22a0e9,0xa9bea7f3,0xaff5ad84,0xaca2ab82,0xb266b131,0xae65ad84,0xb464b399,
0x2f46302c,0x346a350c,0x2d202e33,0x3241338d,0x29f02c0c,0x2f4630f3,0x227b278f,0x27f32ca2,0xa5669c52,0xaaa0a14d,0xab04a8dc,0xb04badf5,0xadaaac96,0xb2e7b19b,0xafcfaebd,0xb4bcb418,
0x304b30ed,0x34bc3568,0x2e0e2f53,0x32b6340c,0x2b042cc8,0x2fcf3150,0x23a82877,0x28452cfa,0xa6619d1b,0xab1da1b2,0xac25a9be,0xb09cae65,0xaeb0ad6b,0xb368b204,0xb09caff5,0xb512b464,
0x30f331ad,0x350c35c4,0x2efb3039,0x332b3452,0x2c0c2d84,0x302c31ad,0x246b2927,0x28902d52,0xa75d9de4,0xab9ba216,0xacc8aaa0,0xb0edaed6,0xafb6ae40,0xb3e8b26c,0xb150b096,0xb568b4b0,
0x355d361e,0x37c63867,0x339f3497,0x359836b4,0x3071320a,0x32913473,0x28dc2daa,0x2b363032,0xac0ca27b,0xae01a4cf,0xb13eaf46,0xb3bdb163,0xb434b2d5,0xb627b506,0xb5beb4fa,0xb826b73e,
0x35ac3678,0x3808388f,0x340934dd,0x35cf36f5,0x30b53266,0x32d534a0,0x29272e01,0x2b82305e,0xac4ba2df,0xae40a502,0xb18eafb6,0xb406b19b,0xb473b33d,0xb663b539,0xb612b545,0xb84cb784,
0x35fb36d0,0x382c38b7,0x34433521,0x36073736,0x30f932c2,0x331834ce,0x29722e59,0x2bcd308a,0xac89a344,0xae7ea534,0xb1dfb013,0xb42eb1d2,0xb4b3b3a5,0xb6a0b56b,0xb666b58f,0xb872b7c9,
0x36493728,0x385038de,0x347c3565,0x363e3776,0x313e331e,0x335c34fa,0x29be2eb0,0x2c0c30b5,0xacc8a3a8,0xaebda566,0xb22fb04b,0xb455b20a,0xb4f1b406,0xb6dcb59d,0xb6b9b5d8,0xb898b807,
0x3697377e,0x38743904,0x34b635a9,0x367537b6,0x3182337a,0x339f3527,0x2a092f08,0x2c3230e1,0xad07a406,0xaefba598,0xb27fb083,0xb47cb241,0xb530b43a,0xb717b5cf,0xb70cb621,0xb8bdb828,
0x36e437d4,0x3897392a,0x34ee35ed,0x36ab37f5,0x31c633d6,0x33e23554,0x2a542f5f,0x2c57310c,0xad45a439,0xaf3aa5cb,0xb2cfb0bb,0xb4a4b279,0xb56eb46d,0xb752b601,0xb75db669,0xb8e1b84a,
0x37303814,0x38b9394e,0x3527362f,0x36e1381a,0x320a3418,0x34123580,0x2aa02fb6,0x2c7d3137,0xad84a46b,0xaf78a5fd,0xb31eb0f3,0xb4cbb2b0,0xb5acb4a0,0xb78cb632,0xb7adb6b1,0xb905b86b,
0x377c383e,0x38db3972,0x355f3672,0x37173838,0x324e3446,0x343435ac,0x2aeb3007,0x2ca23163,0xadc3a49d,0xafb6a62f,0xb36eb12b,0xb4f1b2e7,0xb5eab4d4,0xb7c6b663,0xb7fdb6f8,0xb928b88b,
0x38fd3996,0x39f33a91,0x374c3857,0x3874393e,0x345535d8,0x355d3730,0x2cc8318e,0x2df532e7,0xaff5a661,0xb0f3a7f3,0xb518b31e,0xb649b46a,0xb800b694,0xb8dbb808,0xb94bb8ab,0xba45b99b,
0x391e39b8,0x3a0f3aad,0x37813875,0x388c3959,0x34763604,0x357d375a,0x2cee31b9,0x2e1a3312,0xb01aa694,0xb112a813,0xb53fb356,0xb66fb485,0xb81cb6c5,0xb8f5b81f,0xb96db8cb,0xba61b9b7,
0x393e39da,0x3a2b3ac7,0x37b63893,0x38a53974,0x3497362f,0x359d3784,0x2d1331e5,0x2e40333d,0xb039a6c6,0xb131a82c,0xb565b38d,0xb694b4a0,0xb838b6f5,0xb90fb836,0xb98eb8ea,0xba7cb9d2,
0x395e39fb,0x3a453ae0,0x37ea38b0,0x38bd398e,0x34b9365b,0x35be37ad,0x2d393210,0x2e653368,0xb058a6f8,0xb150a845,0xb58cb3c3,0xb6b9b4bc,0xb854b725,0xb928b84c,0xb9aeb909,0xba97b9ed,
0x397d3a1b,0x3a5f3af9,0x380f38cd,0x38d539a8,0x34da3686,0x35de37d7,0x2d5e323b,0x2e8b3393,0xb077a72a,0xb16fa85e,0xb5b2b3fa,0xb6deb4d7,0xb870b755,0xb941b863,0xb9ceb927,0xbab0ba07,
0x399b3a3a,0x3a793b10,0x382838ea,0x38ed39c1,0x34fa36b1,0x35fe3800,0x2d843266,0x2eb033bd,0xb096a75d,0xb18ea877,0xb5d8b418,0xb703b4f1,0xb88bb784,0xb95ab879,0xb9edb945,0xbac9ba21,
0x39b93a58,0x3a913b26,0x38423906,0x390439da,0x351b36dc,0x361e3814,0x2daa3291,0x2ed633e8,0xb0b5a78f,0xb1ada890,0xb5feb434,0xb728b50c,0xb8a6b7b3,0xb972b88f,0xba0bb962,0xbae0ba3a,
0x39d73a75,0x3aa93b3c,0x385b3922,0x391b39f2,0x353c3706,0x363e3828,0x2dcf32bc,0x2efb3409,0xb0d4a7c1,0xb1cca8aa,0xb624b44f,0xb74cb527,0xb8c1b7e2,0xb98ab8a5,0xba29b97f,0xbaf7ba52,
0x3ac03b50,0x3b5e3bcb,0x39323a0a,0x39de3ab8,0x365e383c,0x375738d7,0x2f21341f,0x302634c8,0xb1eba8c3,0xb2e1a98c,0xb770b542,0xb846b615,0xb9a2b8bb,0xba51b960,0xbb0dba6a,0xbb9cbb11,
0x3ad73b63,0x3b6e3bd6,0x39493a22,0x39f23acb,0x367d3850,0x377638ea,0x2f463434,0x303934dd,0xb20aa8dc,0xb300a9a5,0xb795b55d,0xb857b62f,0xb9b9b8d0,0xba65b974,0xbb22ba81,0xbba9bb24,
0x3aec3b75,0x3b7d3bdf,0x395f3a39,0x3a063ade,0x369d3864,0x379538fd,0x2f6c3449,0x304b34f1,0xb229a8f5,0xb31ea9be,0xb7b8b577,0xb868b649,0xb9d0b8e5,0xba79b987,0xbb36ba97,0xbbb6bb35,
0x3b013b86,0x3b8c3be7,0x39753a4f,0x3a193af0,0x36bc3878,0x37b3390f,0x2f91345e,0x305e3506,0xb247a90e,0xb33da9d7,0xb7dcb592,0xb879b663,0xb9e7b8fa,0xba8cb99a,0xbb4abaad,0xbbc2bb46,
0x3b153b96,0x3b993bee,0x398a3a65,0x3a2d3b02,0x36dc388b,0x37d13921,0x2fb63473,0x3071351b,0xb266a927,0xb35ca9f0,0xb800b5ac,0xb88ab67d,0xb9fdb90f,0xba9fb9ad,0xbb5cbac3,0xbbccbb56,
0x3b283ba5,0x3ba63bf4,0x39a03a7a,0x3a3f3b13,0x36fb389e,0x37ef3933,0x2fdc3488,0x30833530,0xb285a940,0xb37aaa09,0xb811b5c7,0xb89bb697,0xba12b924,0xbab1b9c0,0xbb6dbad7,0xbbd6bb65,
0x3b3b3bb3,0x3bb23bf9,0x39b53a8f,0x3a523b24,0x371a38b2,0x38073945,0x3001349d,0x30963545,0xb2a4a959,0xb399aa22,0xb823b5e1,0xb8abb6b1,0xba28b938,0xbac3b9d2,0xbb7ebaeb,0xbbdfbb74,
0x3b4d3bc0,0x3bbd3bfc,0x39ca3aa4,0x3a643b34,0x373938c5,0x38153957,0x301334b3,0x30a9355a,0xb2c2a972,0xb3b7aa3b,0xb834b5fb,0xb8bcb6ca,0xba3cb94c,0xbad4b9e4,0xbb8dbaff,0xbbe6bb82,
0x20e921b2,0x31313204,0x1ead2020,0x2f14305e,0x1b121d1b,0x2b822d6b,0xe4817db,0x1ead282c,0x997f94b6,0xa9d7a502,0x9de49c52,0xae40ac96,0xa0849f76,0xb0c8afe8,0xa216a14d,0xb26cb19b,
0x275d2845,0x31cc32b6,0x2502262f,0x2fe830e1,0x214d23a8,0x2c322e0e,0x14b61de4,0x1f7628aa,0xa0209b12,0xaa87a598,0xa46ba27b,0xaefbad20,0xa6c6a598,0xb156b06a,0xa890a7f3,0xb32bb241,
0x2a222b1d,0x32663368,0x282c2927,0x305e3163,0x246b2661,0x2ca22eb0,0x17db20e9,0x20202927,0xa2df9de4,0xab36a62f,0xa75da566,0xafb6adaa,0xa9a5a8aa,0xb1e5b0e1,0xab9baaa0,0xb3e8b2e7,
0x2c4b2cfa,0x3300340c,0x29d72b36,0x30c831e5,0x262f2877,0x2d132f53,0x197f22df,0x208429a5,0xa4cfa020,0xabe6a6c6,0xa927a78f,0xb039ae33,0xabe6aa87,0xb273b156,0xad52aca2,0xb452b38d,
0x2d842e65,0x33993464,0x2b822ca2,0x31313266,0x27f329be,0x2d842ff5,0x1b12246b,0x20e92a22,0xa62fa14d,0xac4ba75d,0xaaa0a8dc,0xb096aebd,0xad13ac32,0xb300b1cc,0xaed6adf5,0xb4b0b418,
0x2ebd2fcf,0x341834bc,0x2c962daa,0x319b32e7,0x28dc2b04,0x2df5304b,0x1c522566,0x214d2aa0,0xa78fa27b,0xaca2a7f3,0xac0ca9f0,0xb0f3af46,0xae33ad20,0xb38db241,0xb02caf46,0xb50cb46a,
0x2ff5309c,0x34643512,0x2d6b2eb0,0x32043368,0x29be2c25,0x2e65309c,0x1d1b2661,0x21b22b1d,0xa877a3a8,0xacfaa845,0xacc8ab04,0xb150afcf,0xaf53ae0e,0xb40cb2b6,0xb0edb04b,0xb568b4bc,
0x30963150,0x34b03568,0x2e402fb6,0x326c33e8,0x2aa02cc8,0x2ed630ed,0x1de4275d,0x22162b9b,0xa927a46b,0xad52a890,0xad84ac0c,0xb1adb02c,0xb039aefb,0xb452b32b,0xb1adb0f3,0xb5c4b50c,
0x34fa35be,0x373e3826,0x32d53434,0x35063627,0x2f46313e,0x316333bd,0x227b2c0c,0x24cf2e01,0xadaaa8dc,0xb032ab36,0xb20ab071,0xb473b291,0xb497b39f,0xb6b4b598,0xb61eb55d,0xb867b7c6,
0x35453612,0x3784384c,0x333d3473,0x35393663,0x2fb6318e,0x319b3406,0x22df2c4b,0x25022e40,0xae01a927,0xb05eab82,0xb266b0b5,0xb4a0b2d5,0xb4ddb409,0xb6f5b5cf,0xb678b5ac,0xb88fb808,
0x358f3666,0x37c93872,0x33a534b3,0x356b36a0,0x301331df,0x31d2342e,0x23442c89,0x25342e7e,0xae59a972,0xb08aabcd,0xb2c2b0f9,0xb4ceb318,0xb521b443,0xb736b607,0xb6d0b5fb,0xb8b7b82c,
0x35d836b9,0x38073898,0x340634f1,0x359d36dc,0x304b322f,0x320a3455,0x23a82cc8,0x25662ebd,0xaeb0a9be,0xb0b5ac0c,0xb31eb13e,0xb4fab35c,0xb565b47c,0xb776b63e,0xb728b649,0xb8deb850,
0x3621370c,0x382838bd,0x343a3530,0x35cf3717,0x3083327f,0x3241347c,0x24062d07,0x25982efb,0xaf08aa09,0xb0e1ac32,0xb37ab182,0xb527b39f,0xb5a9b4b6,0xb7b6b675,0xb77eb697,0xb904b874,
0x3669375d,0x384a38e1,0x346d356e,0x36013752,0x30bb32cf,0x327934a4,0x24392d45,0x25cb2f3a,0xaf5faa54,0xb10cac57,0xb3d6b1c6,0xb554b3e2,0xb5edb4ee,0xb7f5b6ab,0xb7d4b6e4,0xb92ab897,
0x36b137ad,0x386b3905,0x34a035ac,0x3632378c,0x30f3331e,0x32b034cb,0x246b2d84,0x25fd2f78,0xafb6aaa0,0xb137ac7d,0xb418b20a,0xb580b412,0xb62fb527,0xb81ab6e1,0xb814b730,0xb94eb8b9,
0x36f837fd,0x388b3928,0x34d435ea,0x366337c6,0x312b336e,0x32e734f1,0x249d2dc3,0x262f2fb6,0xb007aaeb,0xb163aca2,0xb446b24e,0xb5acb434,0xb672b55f,0xb838b717,0xb83eb77c,0xb972b8db,
0x38ab394b,0x399b3a45,0x36943800,0x380838db,0x331e3518,0x346a3649,0x26612ff5,0x27f330f3,0xb18eacc8,0xb2e7adf5,0xb5d8b455,0xb730b55d,0xb857b74c,0xb93eb874,0xb996b8fd,0xba91b9f3,
0x38cb396d,0x39b73a61,0x36c5381c,0x381f38f5,0x3356353f,0x3485366f,0x2694301a,0x28133112,0xb1b9acee,0xb312ae1a,0xb604b476,0xb75ab57d,0xb875b781,0xb959b88c,0xb9b8b91e,0xbaadba0f,
0x38ea398e,0x39d23a7c,0x36f53838,0x3836390f,0x338d3565,0x34a03694,0x26c63039,0x282c3131,0xb1e5ad13,0xb33dae40,0xb62fb497,0xb784b59d,0xb893b7b6,0xb974b8a5,0xb9dab93e,0xbac7ba2b,
0x390939ae,0x39ed3a97,0x37253854,0x384c3928,0x33c3358c,0x34bc36b9,0x26f83058,0x28453150,0xb210ad39,0xb368ae65,0xb65bb4b9,0xb7adb5be,0xb8b0b7ea,0xb98eb8bd,0xb9fbb95e,0xbae0ba45,
0x392739ce,0x3a073ab0,0x37553870,0x38633941,0x33fa35b2,0x34d736de,0x272a3077,0x285e316f,0xb23bad5e,0xb393ae8b,0xb686b4da,0xb7d7b5de,0xb8cdb80f,0xb9a8b8d5,0xba1bb97d,0xbaf9ba5f,
0x394539ed,0x3a213ac9,0x3784388b,0x3879395a,0x341835d8,0x34f13703,0x275d3096,0x2877318e,0xb266ad84,0xb3bdaeb0,0xb6b1b4fa,0xb800b5fe,0xb8eab828,0xb9c1b8ed,0xba3ab99b,0xbb10ba79,
0x39623a0b,0x3a3a3ae0,0x37b338a6,0x388f3972,0x343435fe,0x350c3728,0x278f30b5,0x289031ad,0xb291adaa,0xb3e8aed6,0xb6dcb51b,0xb814b61e,0xb906b842,0xb9dab904,0xba58b9b9,0xbb26ba91,
0x397f3a29,0x3a523af7,0x37e238c1,0x38a5398a,0x344f3624,0x3527374c,0x27c130d4,0x28aa31cc,0xb2bcadcf,0xb409aefb,0xb706b53c,0xb828b63e,0xb922b85b,0xb9f2b91b,0xba75b9d7,0xbb3cbaa9,
0x3a6a3b0d,0x3b113b9c,0x38bb39a2,0x39603a51,0x35423770,0x36153846,0x28c331eb,0x298c32e1,0xb41faf21,0xb4c8b026,0xb83cb65e,0xb8d7b757,0xba0ab932,0xbab8b9de,0xbb50bac0,0xbbcbbb5e,
0x3a813b22,0x3b243ba9,0x38d039b9,0x39743a65,0x355d3795,0x362f3857,0x28dc320a,0x29a53300,0xb434af46,0xb4ddb039,0xb850b67d,0xb8eab776,0xba22b949,0xbacbb9f2,0xbb63bad7,0xbbd6bb6e,
0x3a973b36,0x3b353bb6,0x38e539d0,0x39873a79,0x357737b8,0x36493868,0x28f53229,0x29be331e,0xb449af6c,0xb4f1b04b,0xb864b69d,0xb8fdb795,0xba39b95f,0xbadeba06,0xbb75baec,0xbbdfbb7d,
0x3aad3b4a,0x3b463bc2,0x38fa39e7,0x399a3a8c,0x359237dc,0x36633879,0x290e3247,0x29d7333d,0xb45eaf91,0xb506b05e,0xb878b6bc,0xb90fb7b3,0xba4fb975,0xbaf0ba19,0xbb86bb01,0xbbe7bb8c,
0x3ac33b5c,0x3b563bcc,0x390f39fd,0x39ad3a9f,0x35ac3800,0x367d388a,0x29273266,0x29f0335c,0xb473afb6,0xb51bb071,0xb88bb6dc,0xb921b7d1,0xba65b98a,0xbb02ba2d,0xbb96bb15,0xbbeebb99,
0x3ad73b6d,0x3b653bd6,0x39243a12,0x39c03ab1,0x35c73811,0x3697389b,0x29403285,0x2a09337a,0xb488afdc,0xb530b083,0xb89eb6fb,0xb933b7ef,0xba7ab9a0,0xbb13ba3f,0xbba5bb28,0xbbf4bba6,
0x3aeb3b7e,0x3b743bdf,0x39383a28,0x39d23ac3,0x35e13823,0x36b138ab,0x295932a4,0x2a223399,0xb49db001,0xb545b096,0xb8b2b71a,0xb945b807,0xba8fb9b5,0xbb24ba52,0xbbb3bb3b,0xbbf9bbb2,
0x3aff3b8d,0x3b823be6,0x394c3a3c,0x39e43ad4,0x35fb3834,0x36ca38bc,0x297232c2,0x2a3b33b7,0xb4b3b013,0xb55ab0a9,0xb8c5b739,0xb957b815,0xbaa4b9ca,0xbb34ba64,0xbbc0bb4d,0xbbfcbbbd,
0x39b839ba,0x3a973ab5,0x39b339b5,0x3a583a78,0x39af39b1,0x3a153a37,0x39aa39ad,0x39cd39f2,0x39a639a8,0x398239a8,0x39a139a4,0x3933395b,0x399d399f,0x38e03909,0x3999399b,0x388938b5,
0xb979b972,0xb865b832,0xb986b980,0xb8c7b896,0xb994b98d,0xb924b8f6,0xb9a1b99b,0xb97db951,0xb9afb9a8,0xb9d2b9a8,0xb9bcb9b5,0xba21b9fa,0xb9c9b9c3,0xba6bba47,0xb9d6b9d0,0xbab0ba8e,
0xb9f4b9fe,0xbac7bae9,0xb9dfb9e9,0xba7ebaa3,0xb9c9b9d4,0xba2dba56,0xb9b3b9be,0xb9d6ba02,0xb99db9a8,0xb979b9a8,0xb986b992,0xb916b948,0xb970b97b,0xb8adb8e2,0xb958b964,0xb840b877,
0x39373927,0x381a37b7,0x39583948,0x38943858,0x39793969,0x390738ce,0x39993989,0x3974393e,0x39b839a8,0x39da39a8,0x39d639c7,0x3a393a0b,0x39f439e5,0x3a903a65,0x3a113a02,0x3ade3ab8,
0x3a2d3a3f,0x3af43b1a,0x3a093a1b,0x3aa23acc,0x39e339f6,0x3a453a74,0x39bc39d0,0x39df3a13,0x399439a8,0x397039a8,0x396b3980,0x38f83935,0x39413956,0x387a38ba,0x3916392b,0x37e83838,
0xb8f3b8d8,0xb79bb705,0xb929b90e,0xb85fb817,0xb95db943,0xb8eab8a6,0xb990b976,0xb96bb92b,0xb9c0b9a8,0xb9e3b9a8,0xb9f0b9d8,0xba50ba1b,0xba1dba07,0xbab3ba83,0xba49ba33,0xbb0abae0,
0xba64ba7c,0xbb1ebb46,0xba31ba4b,0xbac4baf3,0xb9fcba17,0xba5cba92,0xb9c5b9e1,0xb9e7ba23,0xb98bb9a8,0xb966b9a8,0xb94fb96d,0xb8dbb922,0xb911b930,0xb845b891,0xb8d1b8f1,0xb74eb7ee,
0x38ad3887,0x36ff364e,0x38f838d3,0x382a37ac,0x3941391d,0x38cc387c,0x39863964,0x39623918,0x39c939a8,0x39eb39a8,0x3a0939e9,0x3a673a2b,0x3a453a27,0x3ad53aa0,0x3a7e3a62,0x3b323b05,
0x3b453b6e,0x3bbc3bdd,0x3ae53b17,0x3b573b8f,0x3a733aae,0x3ac73b14,0x39f03a33,0x3a113a71,0x395d39a8,0x393739a8,0x38bc390e,0x384038bf,0x380f3867,0x365f3775,0x36af376a,0x341a3540,
0xb65fb593,0xb389b115,0xb7e8b726,0xb625b4f9,0xb8adb852,0xb830b748,0xb958b905,0xb933b8b5,0xb9f4b9a8,0xba15b9a8,0xba7eba3b,0xbad1ba78,0xbaf4babc,0xbb63bb20,0xbb57bb28,0xbbc6bb9b,
0xbb68bb91,0xbbd0bbed,0xbb04bb39,0xbb6fbba6,0xba89bac9,0xbadbbb2b,0xb9f8ba43,0xba19ba7f,0xb954b9a8,0xb92eb9a8,0xb89eb8fb,0xb820b8ab,0xb7b2b83d,0xb5ebb71b,0xb60eb6e3,0xb2deb4b1,
0x35bc34d5,0x32322f0e,0x377a369e,0x35b13469,0x388e3828,0x380f36ee,0x394f38f1,0x392938a0,0x39fc39a8,0x3a1d39a8,0x3a933a4b,0x3ae53a87,0x3b133ad6,0x3b7a3b36,0x3b783b49,0x3bd93bb1,
0x3b873baf,0x3be13bf8,0x3b213b58,0x3b853bbb,0x3a9e3ae3,0x3aee3b41,0x3a003a52,0x3a213a8e,0x394a39a8,0x392439a8,0x387f38e7,0x37fe3896,0x37423812,0x357636c1,0x356a3659,0x31853420,
0xb517b414,0xb0d7abd9,0xb70ab614,0xb53ab3ae,0xb86fb7f9,0xb7ddb693,0xb946b8dd,0xb91fb88c,0xba04b9a8,0xba25b9a8,0xbaa9ba5a,0xbaf7ba95,0xbb2fbaf0,0xbb90bb4b,0xbb96bb67,0xbbe8bbc4,
0xbba3bbc9,0xbbefbbff,0xbb3dbb74,0xbb9abbcd,0xbab3bafc,0xbb01bb55,0xba09ba62,0xba29ba9c,0xb941b9a8,0xb91bb9a8,0xb85fb8d3,0xb7bdb881,0xb6d2b7cd,0xb4ffb665,0xb4c3b5ce,0xb029b31b,
0x346f32a1,0x2ef52248,0x36993587,0x34c33288,0x385037a1,0x379b3637,0x393c38c9,0x39163877,0x3a0d39a8,0x3a2d39a8,0x3abd3a69,0x3b0a3aa3,0x3b4a3b08,0x3ba33b5f,0x3bb03b82,0x3bf43bd5,
0x3bf83c00,0x3bf93bd4,0x3bac3bdc,0x3be43bfe,0x3b133b69,0x3b543bab,0x3a313aaa,0x3a503ae0,0x391139a8,0x38ea39a8,0x377a386d,0x366b3817,0x34873608,0x313b348d,0x2d9731f4,0xad65291b,
0xac3828b6,0x2ec33365,0xb44bb160,0xb0bea57f,0xb759b5da,0xb648b45d,0xb90cb862,0xb8e5b80d,0xba35b9a8,0xba54b9a8,0xbb1bbab1,0xbb5cbae6,0xbbb5bb72,0xbbe9bbb2,0xbbfcbbe3,0xbbf5bc00,
0xbbfebbfc,0xbbefbbbc,0xbbbdbbe9,0xbbeebc00,0xbb24bb7b,0xbb63bbb9,0xba39bab8,0xba58baed,0xb907b9a8,0xb8e0b9a8,0xb737b858,0xb625b802,0xb40eb5ab,0xb042b42c,0xa9b1b0cb,0x30109a48,
0x25e4ad7e,0xb0beb475,0x33a23036,0x2f8ba3db,0x3715357c,0x360233f7,0x3902384d,0x38db37ee,0x3a3d39a8,0x3a5c39a8,0x3b2c3abf,0x3b6a3af3,0x3bc53b84,0x3bf23bc0,0x3bff3bee,0x3be93c00,
0x3c003bf4,0x3be23ba0,0x3bcc3bf3,0x3bf53bff,0x3b353b8c,0x3b713bc6,0x3a413ac6,0x3a603af9,0x38fd39a8,0x38d639a8,0x36f43842,0x35df37d8,0x3328354c,0x2e913396,0x16482f40,0xb16ca852,
0x251b304e,0x32193534,0xb2adae14,0xad972aac,0xb6d2b51d,0xb5bcb334,0xb8f8b838,0xb8d1b7c2,0xba45b9a8,0xba64b9a8,0xbb3dbacc,0xbb78baff,0xbbd3bb95,0xbbf8bbcb,0xbc00bbf7,0xbbdabbfd,
0xbbfebbe6,0xbbd2bb80,0xbbd9bbfa,0xbbfbbbfb,0xbb45bb9d,0xbb7fbbd1,0xba49bad3,0xba67bb05,0xb8f3b9a8,0xb8ccb9a8,0xb6afb82d,0xb599b7ac,0xb232b4ed,0xac9cb2d2,0x294dace7,0x32c62c83,
0xac06b1db,0xb371b5f1,0x31b62b75,0x2b43adb0,0x368d34bd,0x3576326f,0x38ee3822,0x38c73796,0x3a4d39a8,0x3a6b39a8,0x3b4c3ad9,0x3b853b0b,0x3bdf3ba4,0x3bfd3bd6,0x3bfc3bfd,0x3bc83bf8,
0x3bbd3b5a,0x3b473a99,0x3bfe3bf4,0x3bf93bbe,0x3b8b3bdb,0x3bb83bf7,0x3a6f3b11,0x3a8c3b3e,0x38c139a8,0x389939a8,0x35523780,0x343236cc,0x294d320d,0xad332de2,0xb40eaedc,0xb6a4b408,
0x346336aa,0x36f438b0,0xa6ad3004,0x2e2d3451,0xb52fb1aa,0xb40ead1a,0xb8bcb76a,0xb894b6b5,0xba73b9a8,0xba90b9a8,0xbb92bb17,0xbbbdbb43,0xbbffbbe0,0xbbf6bbf9,0xbbb2bbf0,0xbb35bbb4,
0xbba5bb30,0xbb21ba5e,0xbc00bbeb,0xbbf3bbaa,0xbb98bbe4,0xbbc2bbfb,0xba76bb1d,0xba93bb49,0xb8b7b9a8,0xb88eb9a8,0xb50bb753,0xb3d3b69e,0xa17fb147,0x2f27ac51,0x34b73099,0x37423499,
0xb50bb75e,0xb790b900,0x9cb6b12e,0xb010b4e1,0x34e730e4,0x33892b11,0x38b2373d,0x38893687,0x3a7a39a8,0x3a9739a8,0x3b9e3b22,0x3bc63b4e,0x3c003be8,0x3bef3bfd,0x3b983be5,0x3b0d3b9e,
0x3b893b02,0x3af73a1f,0x3c003bdf,0x3beb3b93,0x3ba33bec,0x3bcb3bfe,0x3a7e3b28,0x3a9b3b53,0x38ad39a8,0x388439a8,0x34c33726,0x33403670,0xa51b3080,0xb08d297f,0xb55eb1c3,0xb7ddb529,
0x35b13807,0x3815394d,0x28843257,0x31093570,0xb49fb01d,0xb2f7a7da,0xb8a8b710,0xb87fb659,0xba81b9a8,0xba9eb9a8,0xbba9bb2e,0xbbcfbb58,0xbbffbbef,0xbbe6bbff,0xbb7abbd7,0xbae1bb86,
0xbb6abad0,0xbacbb9dc,0xbbfdbbd0,0xbbe1bb79,0xbbaebbf2,0xbbd3bc00,0xba85bb33,0xbaa2bb5d,0xb8a3b9a8,0xb87ab9a8,0xb47bb6f9,0xb2adb642,0x2a7aaf72,0x3185a4b6,0x360232ea,0x383a35b6,
0xb654b85d,0xb85fb996,0xac38b37d,0xb201b5fd,0x34572eaa,0x32631e48,0x389e36e3,0x3874362b,0x3a8939a8,0x3aa539a8,0x3bb33b39,0x3bd73b62,0x3bfc3bf5,0x3bdc3c00,0x3b593bc7,0x3ab33b6b,
0x39b739b9,0x3a883aa6,0x39b239b4,0x3a483a68,0x39ae39b0,0x3a033a26,0x39a939ab,0x39bb39e0,0x39a539a7,0x396e3995,0x39a039a3,0x391e3947,0x399c399e,0x38ca38f5,0x3997399a,0x3873389f,
0xb97cb975,0xb87eb84c,0xb98ab983,0xb8deb8ae,0xb997b991,0xb93bb90d,0xb9a5b99e,0xb993b967,0xb9b2b9ab,0xb9e6b9bd,0xb9bfb9b9,0xba34ba0e,0xb9ccb9c6,0xba7dba59,0xb9d9b9d3,0xbac0ba9f,
0xb9efb9f9,0xbab6bad9,0xb9d9b9e4,0xba6aba91,0xb9c4b9cf,0xba18ba42,0xb9aeb9b9,0xb9bfb9ec,0xb997b9a3,0xb961b991,0xb981b98c,0xb8fcb92f,0xb96ab975,0xb892b8c8,0xb953b95e,0xb824b85c,
0x3940392f,0x383937f6,0x39613950,0x38b13876,0x39813971,0x392338eb,0x39a03991,0x398e395a,0x39bf39b0,0x39f339c1,0x39de39cf,0x3a4f3a22,0x39fb39ec,0x3aa43a7b,0x3a183a0a,0x3af03acb,
0x3a243a36,0x3ae13b07,0x39ff3a12,0x3a8b3ab7,0x39d939ec,0x3a2c3a5d,0x39b239c6,0x39c439f9,0x398a399e,0x3953398c,0x39613975,0x38d93917,0x3936394b,0x3859389a,0x390b3921,0x37a43816,
0xb901b8e6,0xb7e6b750,0xb936b91c,0xb883b83c,0xb96ab950,0xb90bb8c8,0xb99cb983,0xb98ab94b,0xb9ccb9b4,0xb9ffb9c6,0xb9fbb9e4,0xba6aba36,0xba28ba12,0xbacaba9b,0xba53ba3e,0xbb1dbaf5,
0xba57ba70,0xbb09bb33,0xba24ba3e,0xbaabbadc,0xb9efba0a,0xba40ba77,0xb9b7b9d3,0xb9c8ba05,0xb97cb99a,0xb944b988,0xb940b95e,0xb8b6b8fe,0xb901b921,0xb81eb86b,0xb8c0b8e1,0xb6fcb79e,
0x38c0389a,0x375636a7,0x390b38e6,0x38543800,0x3953392f,0x38f238a4,0x39973975,0x3985393d,0x39d939b9,0x3a0c39ca,0x3a1839f9,0x3a843a4a,0x3a533a36,0x3aed3abb,0x3a8b3a70,0x3b473b1c,
0x3b2e3b5a,0x3ba63bce,0x3aca3afe,0x3b373b74,0x3a533a91,0x3a9d3aef,0x39cc3a12,0x39de3a42,0x39363983,0x38fc3971,0x389238e6,0x37fb3880,0x37c5383c,0x35d136eb,0x3651370d,0x330934ae,
0xb6c3b5fa,0xb460b251,0xb824b788,0xb6b8b590,0xb8d9b880,0xb873b7d5,0xb981b92f,0xb96eb8f5,0xba18b9cf,0xba48b9e0,0xba9dba5d,0xbafabaa6,0xbb0fbad9,0xbb80bb43,0xbb6cbb40,0xbbd8bbb2,
0xbb51bb7d,0xbbbdbbe0,0xbae7bb1f,0xbb4ebb8c,0xba66baa9,0xbaafbb04,0xb9d1ba1e,0xb9e2ba4e,0xb928b97e,0xb8edb96c,0xb86eb8cd,0xb7afb866,0xb74bb80b,0xb54fb684,0xb5a2b679,0xb197b411,
0x362e3549,0x338330de,0x37e6370d,0x3651350e,0x38c0385c,0x38593788,0x397c3921,0x396a38e6,0x3a2439d3,0x3a5339e4,0x3ab63a70,0x3b0f3ab7,0x3b2e3af5,0x3b973b5a,0x3b8d3b61,0x3be83bc7,
0x3b703b9c,0x3bd03bef,0x3b033b3d,0x3b653ba2,0x3a793ac1,0x3ac03b19,0x39d53a2a,0x39e63a59,0x3919397a,0x38de3967,0x384938b4,0x3761384c,0x36cf37b4,0x34cc361d,0x34f035e2,0x302332e4,
0xb596b496,0xb244aecf,0xb783b690,0xb5e8b48a,0xb8a7b836,0xb83eb73a,0xb978b912,0xb965b8d7,0xba30b9d7,0xba5fb9e8,0xbacdba82,0xbb23bac8,0xbb4cbb10,0xbbacbb6f,0xbbaabb7f,0xbbf4bbd8,
0xbb8dbbb7,0xbbe0bbf9,0xbb1dbb5a,0xbb7abbb5,0xba8bbad9,0xbad0bb2d,0xb9d9ba36,0xb9eaba65,0xb90bb975,0xb8cfb963,0xb824b89a,0xb713b831,0xb651b750,0xb447b5b3,0xb43bb549,0xad58b1a4,
0x34fc33c0,0x31032bc0,0x371e3611,0x357e3405,0x388d3811,0x382436eb,0x39733903,0x396138c8,0x3a3c39db,0x3a6a39ec,0x3ae43a94,0x3b373ad9,0x3b673b2a,0x3bbe3b83,0x3bc33b9a,0x3bfc3be7,
0x3bed3bff,0x3bff3bea,0x3b8d3bc7,0x3bcc3bf5,0x3ae13b40,0x3b1d3b83,0x39ef3a70,0x39ff3a9b,0x38c0395e,0x3883394b,0x36c33816,0x357e3750,0x33833549,0x2e84332e,0x28cf3061,0xb0aca5b2,
0xaf7ea376,0x29663166,0xb514b2fd,0xb2bfad71,0xb809b69b,0xb734b555,0xb95cb8b9,0xb949b87b,0xba75b9f1,0xbaa1ba01,0xbb49bae9,0xbb8bbb25,0xbbcfbb96,0xbbf9bbd2,0xbc00bbf2,0xbbe3bbfe,
0xbbf6bc00,0xbbfcbbda,0xbb9fbbd6,0xbbd8bbfb,0xbaf0bb52,0xbb2cbb92,0xb9f3ba7b,0xba03baa6,0xb8b1b95a,0xb873b947,0xb673b7f6,0xb52cb718,0xb276b4de,0xac5eb251,0x2052ae39,0x321f2bf2,
0x2cf4a806,0xad3fb2d8,0x34a831ee,0x31e22a93,0x37db364b,0x36fc3502,0x395738a9,0x3944386b,0x3a8039f5,0x3aab3a05,0x3b5b3af8,0x3b993b33,0x3bdd3ba7,0x3bfd3bdd,0x3bff3bfa,0x3bd13bf9,
0x3bfd3bfd,0x3bf53bc6,0x3baf3be3,0x3be23bff,0x3b003b64,0x3b393ba0,0x39f73a86,0x3a083ab0,0x38a23955,0x38633942,0x362237bf,0x34d836e0,0x31663472,0x286b3172,0xaaf82b5c,0xb390ae84,
0xa8cf2cf4,0x2fc93423,0xb43bb0de,0xb103a484,0xb7a4b5fa,0xb6c3b4ae,0xb953b89a,0xb940b85c,0xba8bb9f9,0xbab6ba0a,0xbb6cbb07,0xbba6bb40,0xbbe8bbb7,0xbc00bbe7,0xbbfabbff,0xbbbabbf1,
0xbc00bbf6,0xbbebbbae,0xbbbebbed,0xbbebbc00,0xbb0fbb74,0xbb47bbad,0xb9fbba91,0xba0cbabb,0xb892b950,0xb854b93d,0xb5d1b788,0xb484b6a7,0xb055b405,0x9248b093,0x2e6ba484,0x347e3086,
0x98b6afe2,0xb128b4d8,0x339c2f97,0x3023a420,0x376c35a8,0x368a345a,0x394e388b,0x393b384c,0x3a9639fd,0x3ac03a0e,0x3b7c3b16,0x3bb33b4d,0x3bf23bc5,0x3c003bef,0x3bf03c00,0x3ba03be5,
0x3bde3b91,0x3b8a3af7,0x3bf23bff,0x3c003be3,0x3b533bb9,0x3b823bdf,0x3a103ac5,0x3a203aec,0x38443939,0x38033925,0x342f366d,0x31b03584,0xa8392f65,0xb15a1d7f,0xb531b1c9,0xb7e0b55b,
0x3269358a,0x35a83819,0xae842a61,0x205231e2,0xb651b405,0xb567b15a,0xb936b83c,0xb923b7f6,0xbacaba12,0xbaf0ba22,0xbbbebb5a,0xbbe3bb88,0xbbfdbbf5,0xbbddbc00,0xbb81bbd6,0xbadfbb7c,
0xbbcebb70,0xbb6dbac6,0xbbf8bbfb,0xbbffbbd6,0xbb60bbc4,0xbb8dbbe7,0xba14bacf,0xba24baf5,0xb834b934,0xb7e6b921,0xb3b4b634,0xb103b549,0x2c44ada3,0x326925b2,0x35e23309,0x384135f4,
0xb3a8b63a,0xb63fb869,0x2cc2ad58,0xa89db2f0,0x3617335f,0x352c30ac,0x3931382c,0x391e37d5,0x3ad43a16,0x3afa3a26,0x3bc93b66,0x3bea3b92,0x3bf93bfa,0x3bcf3bff,0x3b5f3bc5,0x3aad3b5d,
0x3bba3b4c,0x3b4d3a93,0x3bfc3bf6,0x3bfd3bc7,0x3b6c3bce,0x3b973bed,0x3a183ad9,0x3a283afe,0x3824392f,0x37c5391c,0x330935fa,0x3055350e,0xae6b2bc0,0xb377aa61,0xb690b423,0xb890b68a,
0x347236e5,0x36d438b6,0xa9fd2f7e,0x2c1233fd,0xb5dcb2b3,0xb4f0affb,0xb92db81c,0xb919b7b4,0xbaddba1a,0xbb03ba2a,0xbbd3bb72,0xbbf0bb9c,0xbbf2bbfe,0xbbbfbbfc,0xbb38bbaf,0xba77bb3c,
0xbba4bb23,0xbb2aba5b,0xbbffbbee,0xbbfabbb6,0xbb77bbd7,0xbba1bbf3,0xba1cbae2,0xba2cbb07,0xb813b92a,0xb7a4b917,0xb25db5bf,0xaf4cb4d2,0x3048a839,0x34412cf4,0x373a34c0,0x38dc371e,
0xb50eb78e,0xb767b901,0x24e9b0d1,0xadd5b484,0x35a23207,0x34b42e9d,0x3928380b,0x39143793,0x3ae73a1e,0x3b0c3a2e,0x3bdb3b7d,0x3bf53ba6,0x3be93c00,0x3bad3bf7,0x3b0d3b97,0x3a3e3b18,
0xb999b996,0xb889b85d,0xb99db99b,0xb8e0b8b5,0xb9a1b99f,0xb933b909,0xb9a6b9a4,0xb982b95b,0xb9aab9a8,0xb9cdb9a8,0xb9afb9ad,0xba15b9f2,0xb9b3b9b1,0xba58ba37,0xb9b8b9b5,0xba97ba78,
0xb9d6b9dc,0xbab0bad0,0xb9c9b9d0,0xba6bba8e,0xb9bcb9c3,0xba21ba47,0xb9afb9b5,0xb9d2b9fa,0xb9a1b9a8,0xb97db9a8,0xb994b99b,0xb924b951,0xb986b98d,0xb8c7b8f6,0xb979b980,0xb865b896,
0x3958394d,0x38403807,0x39703964,0x38ad3877,0x3986397b,0x391638e2,0x399d3992,0x39793948,0x39b339a8,0x39d639a8,0x39c939be,0x3a2d3a02,0x39df39d4,0x3a7e3a56,0x39f439e9,0x3ac73aa3,
0x3a113a1f,0x3ade3b02,0x39f43a02,0x3a903ab8,0x39d639e5,0x3a393a65,0x39b839c7,0x39da3a0b,0x399939a8,0x397439a8,0x39793989,0x3907393e,0x39583969,0x389438ce,0x39373948,0x381a3858,
0xb916b900,0xb7e8b75e,0xb941b92b,0xb87ab838,0xb96bb956,0xb8f8b8ba,0xb994b980,0xb970b935,0xb9bcb9a8,0xb9dfb9a8,0xb9e3b9d0,0xba45ba13,0xba09b9f6,0xbaa2ba74,0xba2dba1b,0xbaf4bacc,
0xba49ba5e,0xbb0abb30,0xba1dba33,0xbab3bae0,0xb9f0ba07,0xba50ba83,0xb9c0b9d8,0xb9e3ba1b,0xb990b9a8,0xb96bb9a8,0xb95db976,0xb8eab92b,0xb929b943,0xb85fb8a6,0xb8f3b90e,0xb79bb817,
0x38d138b0,0x374e36aa,0x391138f1,0x384537ee,0x394f3930,0x38db3891,0x398b396d,0x39663922,0x39c539a8,0x39e739a8,0x39fc39e1,0x3a5c3a23,0x3a313a17,0x3ac43a92,0x3a643a4b,0x3b1e3af3,
0x3a7e3a99,0x3b323b5a,0x3a453a62,0x3ad53b05,0x3a093a27,0x3a673aa0,0x39c939e9,0x39eb3a2b,0x398639a8,0x396239a8,0x39413964,0x38cc3918,0x38f8391d,0x382a387c,0x38ad38d3,0x36ff37ac,
0xb6afb5f1,0xb41ab1db,0xb80fb76a,0xb65fb540,0xb8bcb867,0xb840b775,0xb95db90e,0xb937b8bf,0xb9f0b9a8,0xba11b9a8,0xba73ba33,0xbac7ba71,0xbae5baae,0xbb57bb14,0xbb45bb17,0xbbbcbb8f,
0xbb57bb80,0xbbc6bbe6,0xbaf4bb28,0xbb63bb9b,0xba7ebabc,0xbad1bb20,0xb9f4ba3b,0xba15ba78,0xb958b9a8,0xb933b9a8,0xb8adb905,0xb830b8b5,0xb7e8b852,0xb625b748,0xb65fb726,0xb389b4f9,
0x360e3534,0x32de304e,0x37b236e3,0x35eb34b1,0x389e383d,0x3820371b,0x395438fb,0x392e38ab,0x39f839a8,0x3a1939a8,0x3a893a43,0x3adb3a7f,0x3b043ac9,0x3b6f3b2b,0x3b683b39,0x3bd03ba6,
0x3b783ba0,0x3bd93bf4,0x3b133b49,0x3b7a3bb1,0x3a933ad6,0x3ae53b36,0x39fc3a4b,0x3a1d3a87,0x394f39a8,0x392939a8,0x388e38f1,0x380f38a0,0x377a3828,0x35b136ee,0x35bc369e,0x32323469,
0xb56ab475,0xb185ad7e,0xb742b659,0xb576b420,0xb87fb812,0xb7feb6c1,0xb94ab8e7,0xb924b896,0xba00b9a8,0xba21b9a8,0xba9eba52,0xbaeeba8e,0xbb21bae3,0xbb85bb41,0xbb87bb58,0xbbe1bbbb,
0xbb96bbbc,0xbbe8bbfc,0xbb2fbb67,0xbb90bbc4,0xbaa9baf0,0xbaf7bb4b,0xba04ba5a,0xba25ba95,0xb946b9a8,0xb91fb9a8,0xb86fb8dd,0xb7ddb88c,0xb70ab7f9,0xb53ab693,0xb517b614,0xb0d7b3ae,
0x34c33365,0x302928b6,0x36d235ce,0x34ff331b,0x385f37cd,0x37bd3665,0x394138d3,0x391b3881,0x3a0939a8,0x3a2939a8,0x3ab33a62,0x3b013a9c,0x3b3d3afc,0x3b9a3b55,0x3ba33b74,0x3bef3bcd,
0x3bb03bd4,0x3bf43c00,0x3b4a3b82,0x3ba33bd5,0x3abd3b08,0x3b0a3b5f,0x3a0d3a69,0x3a2d3aa3,0x393c39a8,0x391639a8,0x385038c9,0x379b3877,0x369937a1,0x34c33637,0x346f3587,0x2ef53288,
0xad972248,0x2d6532a1,0xb487b1f4,0xb13ba91b,0xb77ab608,0xb66bb48d,0xb911b86d,0xb8eab817,0xba31b9a8,0xba50b9a8,0xbb13baaa,0xbb54bae0,0xbbacbb69,0xbbe4bbab,0xbbf8bbdc,0xbbf9bbfe,
0xbbfcbbff,0xbbf5bbc9,0xbbb5bbe3,0xbbe9bc00,0xbb1bbb72,0xbb5cbbb2,0xba35bab1,0xba54bae6,0xb90cb9a8,0xb8e5b9a8,0xb759b862,0xb648b80d,0xb44bb5da,0xb0beb45d,0xac38b160,0x2ec3a57f,
0x29b1abd9,0xb010b414,0x340e30cb,0x30421a48,0x373735ab,0x3625342c,0x39073858,0x38e03802,0x3a3939a8,0x3a5839a8,0x3b243ab8,0x3b633aed,0x3bbd3b7b,0x3bee3bb9,0x3bfe3be9,0x3bef3c00,
0x3bff3bf8,0x3be93baf,0x3bc53bee,0x3bf23c00,0x3b2c3b84,0x3b6a3bc0,0x3a3d3abf,0x3a5c3af3,0x390239a8,0x38db39a8,0x3715384d,0x360237ee,0x33a2357c,0x2f8b33f7,0x25e43036,0xb0bea3db,
0x96482f0e,0x316c34d5,0xb328af40,0xae912852,0xb6f4b54c,0xb5dfb396,0xb8fdb842,0xb8d6b7d8,0xba41b9a8,0xba60b9a8,0xbb35bac6,0xbb71baf9,0xbbccbb8c,0xbbf5bbc6,0xbc00bbf3,0xbbe2bbff,
0xbc00bbed,0xbbdabb91,0xbbd3bbf7,0xbbf8bbfd,0xbb3dbb95,0xbb78bbcb,0xba45bacc,0xba64baff,0xb8f8b9a8,0xb8d1b9a8,0xb6d2b838,0xb5bcb7c2,0xb2adb51d,0xad97b334,0x251bae14,0x32192aac,
0xa94db115,0xb2c6b593,0x32322ce7,0x2c9cac83,0x36af34ed,0x359932d2,0x38f3382d,0x38cc37ac,0x3a4939a8,0x3a6739a8,0x3b453ad3,0x3b7f3b05,0x3bd93b9d,0x3bfb3bd1,0x3bfe3bfa,0x3bd23bfb,
0x3bfc3bdd,0x3bc83b6e,0x3bdf3bfd,0x3bfd3bf8,0x3b4c3ba4,0x3b853bd6,0x3a4d3ad9,0x3a6b3b0b,0x38ee39a8,0x38c739a8,0x368d3822,0x35763796,0x31b634bd,0x2b43326f,0xac062b75,0xb371adb0,
0x340e364e,0x36a43887,0xa94d2edc,0x2d333408,0xb552b20d,0xb432ade2,0xb8c1b780,0xb899b6cc,0xba6fb9a8,0xba8cb9a8,0xbb8bbb11,0xbbb8bb3e,0xbbfebbdb,0xbbf9bbf7,0xbbbdbbf4,0xbb47bbbe,
0xbbb2bb46,0xbb35ba7c,0xbbffbbf0,0xbbf6bbb4,0xbb92bbe0,0xbbbdbbf9,0xba73bb17,0xba90bb43,0xb8bcb9a8,0xb894b9a8,0xb52fb76a,0xb40eb6b5,0xa6adb1aa,0x2e2dad1a,0x34633004,0x36f43451,
0xb4b7b705,0xb742b8d8,0x217fb099,0xaf27b499,0x350b3147,0x33d32c51,0x38b73753,0x388e369e,0x3a7639a8,0x3a9339a8,0x3b983b1d,0x3bc23b49,0x3c003be4,0x3bf33bfb,0x3ba53beb,0x3b213baa,
0x3b983b1a,0x3b0d3a3f,0x3c003be5,0x3bef3b9e,0x3b9e3be8,0x3bc63bfd,0x3a7a3b22,0x3a973b4e,0x38b239a8,0x388939a8,0x34e7373d,0x33893687,0x9cb630e4,0xb0102b11,0xb50bb12e,0xb790b4e1,
0x355e37b7,0x37dd3927,0x251b31c3,0x308d3529,0xb4c3b080,0xb340a97f,0xb8adb726,0xb884b670,0xba7eb9a8,0xba9bb9a8,0xbba3bb28,0xbbcbbb53,0xbc00bbec,0xbbebbbfe,0xbb89bbdf,0xbaf7bb93,
0xbb7abae9,0xbae1b9fe,0xbbffbbd7,0xbbe6bb86,0xbba9bbef,0xbbcfbbff,0xba81bb2e,0xba9ebb58,0xb8a8b9a8,0xb87fb9a8,0xb49fb710,0xb2f7b659,0x2884b01d,0x3109a7da,0x35b13257,0x38153570,
0xb602b832,0xb83ab972,0xaa7ab2ea,0xb185b5b6,0x347b2f72,0x32ad24b6,0x38a336f9,0x387a3642,0x3a8539a8,0x3aa239a8,0x3bae3b33,0x3bd33b5d,0x3bfd3bf2,0x3be13c00,0x3b6a3bd0,0x3acb3b79,
0x3b593ab5,0x3ab339ba,0x3bfc3bc7,0x3bdc3b6b,0x3bb33bf5,0x3bd73c00,0x3a893b39,0x3aa53b62,0x389e39a8,0x387439a8,0x345736e3,0x3263362b,0xac382eaa,0xb2011e48,0xb654b37d,0xb85fb5fd,
0xb99ab997,0xb89fb873,0xb99eb99c,0xb8f5b8ca,0xb9a3b9a0,0xb947b91e,0xb9a7b9a5,0xb995b96e,0xb9abb9a9,0xb9e0b9bb,0xb9b0b9ae,0xba26ba03,0xb9b4b9b2,0xba68ba48,0xb9b9b9b7,0xbaa6ba88,
0xb9d3b9d9,0xba9fbac0,0xb9c6b9cc,0xba59ba7d,0xb9b9b9bf,0xba0eba34,0xb9abb9b2,0xb9bdb9e6,0xb99eb9a5,0xb967b993,0xb991b997,0xb90db93b,0xb983b98a,0xb8aeb8de,0xb975b97c,0xb84cb87e,
0x395e3953,0x385c3824,0x3975396a,0x38c83892,0x398c3981,0x392f38fc,0x39a33997,0x39913961,0x39b939ae,0x39ec39bf,0x39cf39c4,0x3a423a18,0x39e439d9,0x3a913a6a,0x39f939ef,0x3ad93ab6,
0x3a0a3a18,0x3acb3af0,0x39ec39fb,0x3a7b3aa4,0x39cf39de,0x3a223a4f,0x39b039bf,0x39c139f3,0x399139a0,0x395a398e,0x39713981,0x38eb3923,0x39503961,0x387638b1,0x392f3940,0x37f63839,
0xb921b90b,0xb816b7a4,0xb94bb936,0xb89ab859,0xb975b961,0xb917b8d9,0xb99eb98a,0xb98cb953,0xb9c6b9b2,0xb9f9b9c4,0xb9ecb9d9,0xba5dba2c,0xba12b9ff,0xbab7ba8b,0xba36ba24,0xbb07bae1,
0xba3eba53,0xbaf5bb1d,0xba12ba28,0xba9bbaca,0xb9e4b9fb,0xba36ba6a,0xb9b4b9cc,0xb9c6b9ff,0xb983b99c,0xb94bb98a,0xb950b96a,0xb8c8b90b,0xb91cb936,0xb83cb883,0xb8e6b901,0xb750b7e6,
0x38e138c0,0x379e36fc,0x39213901,0x386b381e,0x395e3940,0x38fe38b6,0x399a397c,0x39883944,0x39d339b7,0x3a0539c8,0x3a0a39ef,0x3a773a40,0x3a3e3a24,0x3adc3aab,0x3a703a57,0x3b333b09,
0x3a703a8b,0x3b1c3b47,0x3a363a53,0x3abb3aed,0x39f93a18,0x3a4a3a84,0x39b939d9,0x39ca3a0c,0x39753997,0x393d3985,0x392f3953,0x38a438f2,0x38e6390b,0x38003854,0x389a38c0,0x36a73756,
0xb70db651,0xb4aeb309,0xb83cb7c5,0xb6ebb5d1,0xb8e6b892,0xb880b7fb,0xb983b936,0xb971b8fc,0xba12b9cc,0xba42b9de,0xba91ba53,0xbaefba9d,0xbafebaca,0xbb74bb37,0xbb5abb2e,0xbbcebba6,
0xbb40bb6c,0xbbb2bbd8,0xbad9bb0f,0xbb43bb80,0xba5dba9d,0xbaa6bafa,0xb9cfba18,0xb9e0ba48,0xb92fb981,0xb8f5b96e,0xb880b8d9,0xb7d5b873,0xb788b824,0xb590b6b8,0xb5fab6c3,0xb251b460,
0x367935a2,0x34113197,0x380b374b,0x3684354f,0x38cd386e,0x386637af,0x397e3928,0x396c38ed,0x3a1e39d1,0x3a4e39e2,0x3aa93a66,0x3b043aaf,0x3b1f3ae7,0x3b8c3b4e,0x3b7d3b51,0x3be03bbd,
0x3b613b8d,0x3bc73be8,0x3af53b2e,0x3b5a3b97,0x3a703ab6,0x3ab73b0f,0x39d33a24,0x39e43a53,0x3921397c,0x38e6396a,0x385c38c0,0x37883859,0x370d37e6,0x350e3651,0x3549362e,0x30de3383,
0xb5e2b4f0,0xb2e4b023,0xb7b4b6cf,0xb61db4cc,0xb8b4b849,0xb84cb761,0xb97ab919,0xb967b8de,0xba2ab9d5,0xba59b9e6,0xbac1ba79,0xbb19bac0,0xbb3dbb03,0xbba2bb65,0xbb9cbb70,0xbbefbbd0,
0xbb7fbbaa,0xbbd8bbf4,0xbb10bb4c,0xbb6fbbac,0xba82bacd,0xbac8bb23,0xb9d7ba30,0xb9e8ba5f,0xb912b978,0xb8d7b965,0xb836b8a7,0xb73ab83e,0xb690b783,0xb48ab5e8,0xb496b596,0xaecfb244,
0x3549343b,0x31a42d58,0x37503651,0x35b33447,0x389a3824,0x38313713,0x3975390b,0x396338cf,0x3a3639d9,0x3a6539ea,0x3ad93a8b,0x3b2d3ad0,0x3b5a3b1d,0x3bb53b7a,0x3bb73b8d,0x3bf93be0,
0x3b9a3bc3,0x3be73bfc,0x3b2a3b67,0x3b833bbe,0x3a943ae4,0x3ad93b37,0x39db3a3c,0x39ec3a6a,0x39033973,0x38c83961,0x3811388d,0x36eb3824,0x3611371e,0x3405357e,0x33c034fc,0x2bc03103,
0xb061a8cf,0x25b230ac,0xb549b383,0xb32eae84,0xb816b6c3,0xb750b57e,0xb95eb8c0,0xb94bb883,0xba70b9ef,0xba9bb9ff,0xbb40bae1,0xbb83bb1d,0xbbc7bb8d,0xbbf5bbcc,0xbbffbbed,0xbbeabbff,
0xbbf2bc00,0xbbfebbe3,0xbb96bbcf,0xbbd2bbf9,0xbae9bb49,0xbb25bb8b,0xb9f1ba75,0xba01baa1,0xb8b9b95c,0xb87bb949,0xb69bb809,0xb555b734,0xb2fdb514,0xad71b2bf,0xa376af7e,0x31662966,
0x2e39a052,0xabf2b21f,0x34de3276,0x32512c5e,0x37f63673,0x3718352c,0x395a38b1,0x39473873,0x3a7b39f3,0x3aa63a03,0x3b523af0,0x3b923b2c,0x3bd63b9f,0x3bfb3bd8,0x3c003bf6,0x3bda3bfc,
0x3bfa3bff,0x3bf93bd1,0x3ba73bdd,0x3bdd3bfd,0x3af83b5b,0x3b333b99,0x39f53a80,0x3a053aab,0x38a93957,0x386b3944,0x364b37db,0x350236fc,0x31ee34a8,0x2a9331e2,0xa8062cf4,0xb2d8ad3f,
0xab5c2af8,0x2e843390,0xb472b166,0xb172a86b,0xb7bfb622,0xb6e0b4d8,0xb955b8a2,0xb942b863,0xba86b9f7,0xbab0ba08,0xbb64bb00,0xbba0bb39,0xbbe3bbaf,0xbbffbbe2,0xbbfdbbfd,0xbbc6bbf5,
0xbbffbbfa,0xbbf1bbba,0xbbb7bbe8,0xbbe7bc00,0xbb07bb6c,0xbb40bba6,0xb9f9ba8b,0xba0abab6,0xb89ab953,0xb85cb940,0xb5fab7a4,0xb4aeb6c3,0xb0deb43b,0xa484b103,0x2cf4a8cf,0x34232fc9,
0x2484ae6b,0xb086b47e,0x34053055,0x30931248,0x378835d1,0x36a73484,0x39503892,0x393d3854,0x3a9139fb,0x3abb3a0c,0x3b743b0f,0x3bad3b47,0x3bed3bbe,0x3c003beb,0x3bf63c00,0x3bae3beb,
0x3c003bf0,0x3be53ba0,0x3bc53bf2,0x3bef3c00,0x3b163b7c,0x3b4d3bb3,0x39fd3a96,0x3a0e3ac0,0x388b394e,0x384c393b,0x35a8376c,0x345a368a,0x2f97339c,0xa4203023,0xafe298b6,0xb4d8b128,
0x31c93531,0x355b37e0,0xaf652839,0x9d7f315a,0xb66db42f,0xb584b1b0,0xb939b844,0xb925b803,0xbac5ba10,0xbaecba20,0xbbb9bb53,0xbbdfbb82,0xbbffbbf2,0xbbe3bc00,0xbb91bbde,0xbaf7bb8a,
0xbbd6bb81,0xbb7cbadf,0xbbf5bbfd,0xbc00bbdd,0xbb5abbbe,0xbb88bbe3,0xba12baca,0xba22baf0,0xb83cb936,0xb7f6b923,0xb405b651,0xb15ab567,0x2a61ae84,0x31e22052,0x358a3269,0x381935a8,
0xb309b5e2,0xb5f4b841,0x2da3ac44,0xa5b2b269,0x363433b4,0x35493103,0x39343834,0x392137e6,0x3acf3a14,0x3af53a24,0x3bc43b60,0x3be73b8d,0x3bfb3bf8,0x3bd63bff,0x3b703bce,0x3ac63b6d,
0x3bc53b5f,0x3b5d3aad,0x3bfa3bf9,0x3bff3bcf,0x3b663bc9,0x3b923bea,0x3a163ad4,0x3a263afa,0x382c3931,0x37d5391e,0x335f3617,0x30ac352c,0xad582cc2,0xb2f0a89d,0xb63ab3a8,0xb869b63f,
0x34233690,0x368a3890,0xabc02e6b,0x2a613377,0xb5fab309,0xb50eb055,0xb92fb824,0xb91cb7c5,0xbad9ba18,0xbafeba28,0xbbcebb6c,0xbbedbb97,0xbbf6bbfc,0xbbc7bbfd,0xbb4cbbba,0xba93bb4d,
0xbbafbb38,0xbb3cba77,0xbbfebbf2,0xbbfcbbbf,0xbb72bbd3,0xbb9cbbf0,0xba1abadd,0xba2abb03,0xb81cb92d,0xb7b4b919,0xb2b3b5dc,0xaffbb4f0,0x2f7ea9fd,0x33fd2c12,0x36e53472,0x38b636d4,
0xb4c0b73a,0xb71eb8dc,0x2839b048,0xacf4b441,0x35bf325d,0x34d22f4c,0x392a3813,0x391737a4,0x3ae23a1c,0x3b073a2c,0x3bd73b77,0x3bf33ba1,0x3bee3bff,0x3bb63bfa,0x3b233ba4,0x3a5b3b2a,
0x3b973b0d,0x3b183a3e,0x3c003be9,0x3bf73bad,0x3b7d3bdb,0x3ba63bf5,0x3a1e3ae7,0x3a2e3b0c,0x380b3928,0x37933914,0x320735a2,0x2e9d34b4,0xb0d124e9,0xb484add5,0xb78eb50e,0xb901b767,
0xb97239ba,0x39dc3996,0xb8323ab5,0x3ad0385d,0x3927b9fe,0xba1fb94d,0x37b7bae9,0xbb02b807,0xb8d83a3f,0x3a5e3900,0xb7053b1a,0x3b30375e,0x3887ba7c,0xba99b8b0,0x364ebb46,0xbb5ab6aa,
0xb90039dc,0x3a3f3972,0xad7e3be6,0x3bf83115,0x3807ba99,0xbae9b887,0xabd9bc00,0xbbfca248,0xb5f13b30,0x3b6e3705,0x32a13bed,0x3bd4b04e,0x3365bba0,0xbbc9b4d5,0xb593bbaf,0xbb803475,
0xb88739fe,0x3a99394d,0x35f13bbc,0x3b6eb414,0x3593bb1a,0xbb80b75e,0xb8b0bb02,0xba7c37b7,0xaf0e3bc9,0x3bf43365,0x3a1f39dc,0x3927b972,0xb04ebc00,0xbbed2248,0xbb30b85d,0xb7053ab5,
0xb8073a1f,0x3ae93927,0x39fe3a3f,0x394db900,0x31dbbb80,0xbbddb593,0xbb6eb832,0xb5f13ad0,0x31153c00,0x3be62248,0x3bff32a1,0x28b6bbd4,0xb7b7bb91,0xbb023534,0xbba0304e,0x34d53bed,
0xb7053a3f,0x3b303900,0x3bbc375e,0x3414bb1a,0x2248bbc9,0xbc00b365,0xbbdda8b6,0x31db3bff,0x36aa3bd4,0x3b46b2a1,0x3a7cb64e,0xb8b0bb5a,0xba1fba5e,0xb92738d8,0xb7b739fe,0x3b02394d,
0xb5f13a5e,0x3b6e38d8,0x3bd42bd9,0xb2a1bbfc,0xb115bbf4,0xbbe6af0e,0xb9dc375e,0x39723b1a,0x39273b46,0x3a1fb6aa,0x3475bad0,0xbbafb832,0xbb91b887,0xb5343a99,0x34143c00,0x3bbc2248,
0xb4d53a7c,0x3ba038b0,0x3a3fb593,0xb900bb80,0xb534bc00,0xbb912248,0xb4143ab5,0x3bbc385d,0x3a993a5e,0x3887b8d8,0xb5f1bbfc,0xbb6e2bd9,0xbbffb475,0x28b63baf,0x3ad03a1f,0x3832b927,
0xb3653a99,0x3bc93887,0x36aab996,0xbb46b9ba,0xb7b7bbed,0xbb02304e,0x34d53bfc,0x3ba02bd9,0x3b913927,0x3534ba1f,0xbae9ba3f,0xb8073900,0xbb5a28b6,0x364e3bff,0x3bd43115,0xb2a1bbe6,
0xb1153ab5,0x3be6385d,0xa8b6bb6e,0xbbffb5f1,0xb900bbbc,0xba3f3414,0x3a1f3b30,0x3927b705,0x3bfc375e,0x2bd9bb1a,0xbbedb475,0x304e3baf,0xb9ba3593,0x39963b80,0x3887b832,0xba99bad0,
0xad7e3ad0,0x3bf83832,0xb7b7bbff,0xbb0228b6,0xb9febb6e,0xb94d35f1,0x3bed3887,0x304eba99,0x3bd43414,0xb2a1bbbc,0xb9963534,0x39ba3b91,0xb6aa3900,0x3b463a3f,0xb115bba0,0xbbe6b4d5,
0xa2483ae9,0x3c003807,0xba99bb30,0xb8873705,0xbad0bb02,0xb83237b7,0x3b462d7e,0xb6aabbf8,0x3b1a28b6,0xb75ebbff,0xaf0e3a7c,0x3bf438b0,0xabd93ab5,0x3bfc385d,0xba5ebb5a,0xb8d8364e,
0x2bd93b02,0x3bfc37b7,0xbbedb927,0xb04e3a1f,0xbb6eba7c,0xb5f138b0,0x385db6aa,0xbab5bb46,0x39dcb1db,0xb972bbdd,0x38323c00,0x3ad02248,0x34d53bbc,0x3ba03414,0xbbf4b705,0x2f0e3b30,
0x304e3b1a,0x3bed375e,0xbb91b475,0x35343baf,0xbbd4b9dc,0xb2a13972,0x2248ba7c,0xbc00b8b0,0x3832b64e,0xbad0bb5a,0x3b803a99,0x3593b887,0x39003bfc,0x3a3fabd9,0xb9273414,0x3a1f3bbc,
0x32a13b30,0x3bd43705,0xb996304e,0x39ba3bed,0xbbffb927,0xa8b63a1f,0xb832bbf4,0xbad0af0e,0x3475b8b0,0xbbafba7c,0x3ba03593,0xb4d5bb80,0x3ae93b6e,0x3807b5f1,0x2bd93a99,0x3bfc3887,
0x34753b46,0x3baf36aa,0xb4d53832,0x3ba03ad0,0xbbedb85d,0x304e3ab5,0xbb30bb5a,0xb705364e,0x2248b9fe,0xbc00b94d,0x3887b414,0xba99bbbc,0x3be63a1f,0x3115b927,0x39dc3bf4,0x3972af0e,
0x35933b5a,0x3b80364e,0x31153a99,0x3be63887,0xbba0b705,0x34d53b30,0xbbf4b8d8,0x2f0e3a5e,0xb414bb02,0xbbbcb7b7,0xabd9ba1f,0xbbfcb927,0x3bd43832,0xb2a1bad0,0x3c003972,0xa248b9dc,
0x36aa3b6e,0x3b4635f1,0x38b03bdd,0x3a7c31db,0xbb1ab534,0x375e3b91,0xba3fb04e,0x39003bed,0xb807bbaf,0xbae9b475,0xb94dbbf8,0xb9fead7e,0x3ab53365,0xb85dbbc9,0x39ba28b6,0xb996bbff,
0x37b73b80,0x3b023593,0x3b1a3bc9,0x375eb365,0xba5eb2a1,0x38d83bd4,0xb53435f1,0x3b913b6e,0xb9babbfc,0xb996abd9,0xbbddbae9,0xb1db3807,0x38b0ad7e,0xba7cbbf8,0x28b6b900,0xbbffba3f,
0x385d3b91,0x3ab53534,0x3c003a5e,0x2248b8d8,0xb972ad7e,0x39dc3bf8,0x33653a3f,0x3bc93900,0xbb02bbe6,0xb7b73115,0xbb1ab6aa,0x375e3b46,0x3414b64e,0xbbbcbb5a,0xb94dbbdd,0xb9feb1db,
0x38d83ba0,0x3a5e34d5,0x3b3037b7,0xb705bb02,0xb85d28b6,0x3ab53bff,0x39ba3be6,0x39963115,0xbbc9bb6e,0xb36535f1,0xb6aa31db,0x3b463bdd,0xaf0eb94d,0xbbf4b9fe,0xbbf8bae9,0xad7e3807,
0x394d3baf,0x39fe3475,0x38d82d7e,0xba5ebbf8,0xb64e3115,0x3b5a3be6,0x3bd43b80,0x32a1b593,0xbbffba99,0x28b63887,0x336539ba,0x3bc93996,0xb75ebae9,0xbb1ab807,0xba3fb534,0x39003b91,
0x39ba3bbc,0x39963414,0x31dbb534,0xbbddbb91,0xb3653475,0x3bc93baf,0x3b803927,0xb593ba1f,0xbba0b972,0x34d539dc,0x3a3f3be6,0x39003115,0xb9febbd4,0xb94db2a1,0xb04e35f1,0x3bed3b6e,
0x3a1f3bc9,0x39273365,0xb475b972,0xbbafb9dc,0xabd9364e,0x3bfc3b5a,0x38d831db,0xba5ebbdd,0xbab5b807,0x385d3ae9,0x3c003b30,0x2248b705,0xbb80bbf4,0xb5932f0e,0x38b03b1a,0x3a7c375e,
0x3a7c3bd4,0x38b032a1,0xb972bb5a,0xb9dcb64e,0x2f0e3807,0x3bf43ae9,0x2d7eb534,0xbbf8bb91,0xb94db4d5,0x39fe3ba0,0x3a5e37b7,0xb8d8bb02,0xbc00bb46,0x224836aa,0x3bdd3bc9,0x31dbb365,
0x3ad03bdd,0x383231db,0xbb80bc00,0xb5932248,0x347538d8,0x3baf3a5e,0xb75eb9fe,0xbb1ab94d,0xb705ad7e,0x3b303bf8,0x3414af0e,0xbbbcbbf4,0xbb6eb9dc,0x35f13972,0x3ab538b0,0xb85dba7c,
0x3b1a3be6,0x375e3115,0xbbf4bb46,0x2f0e36aa,0x37053996,0x3b3039ba,0xbae9bbd4,0xb807b2a1,0xb1db304e,0x3bdd3bed,0xb64eb94d,0xbb5ab9fe,0xb9dcb7b7,0x39723b02,0x3365ad7e,0xbbc9bbf8,
0x3b5a3bed,0x364e304e,0xbab5b94d,0x385d39fe,0x38b03a3f,0x3a7c3900,0xbbffbba0,0x28b634d5,0x2d7e3593,0x3bf83b80,0xbb02bbc9,0xb7b7b365,0xb705b1db,0x3b303bdd,0xb807b9ba,0xbae9b996,
0x3b913bf4,0x35342f0e,0xb807b4d5,0x3ae93ba0,0x39ba3ad0,0x39963832,0xba99b972,0x388739dc,0x3593385d,0x3b803ab5,0xbbe6bb6e,0x311535f1,0xad7e304e,0x3bf83bed,0xbbafbbfc,0xb475abd9,
0x3bbc3bf8,0x34142d7e,0xabd92f0e,0x3bfc3bf4,0x3a993b46,0x388736aa,0xb64eb365,0x3b5a3bc9,0x38b039ba,0x3a7c3996,0xb972b85d,0x39dc3ab5,0x34753705,0x3baf3b30,0xbb1aba5e,0x375e38d8,
0x3bdd3bfc,0x31db2bd9,0x364e3807,0x3b5a3ae9,0x3b463ba0,0x36aa34d5,0x31153475,0x3be63baf,0x3a3f3ad0,0x39003832,0xad7e28b6,0x3bf83bff,0x38d83996,0x3a5e39ba,0xb534b2a1,0x3b913bd4,
0x3bf43bff,0x2f0e28b6,0x3a1f3a7c,0x392738b0,0x3bbc3bdd,0x341431db,0x394d39ba,0x39fe3996,0x3b5a3b91,0x364e3534,0x385d38d8,0x3ab53a5e,0x3ad03b1a,0x3832375e,0x36aa37b7,0x3b463b02,
0x3bff3c00,0x28b62248,0x3bc93bd4,0x336532a1,0x3bf83bfc,0x2d7e2bd9,0x3baf3bbc,0x34753414,0x3bed3bf4,0x304e2f0e,0x3b913ba0,0x353434d5,0x3bdd3be6,0x31db3115,0x3b6e3b80,0x35f13593,
0xb5933b6e,0x3b8035f1,0xb1153bdd,0x3be631db,0x34d5bb91,0xbba0b534,0x2f0ebbed,0xbbf4b04e,0xb4143baf,0x3bbc3475,0xabd93bf8,0x3bfc2d7e,0x32a1bbc9,0xbbd4b365,0x2248bbff,0xbc00a8b6,
0x37b73b46,0x3b02b6aa,0x3b1a3832,0x375ebad0,0xb8d8bab5,0xba5e385d,0xbb91b64e,0xb5343b5a,0x39ba39fe,0x3996b94d,0x3bdd3414,0x31dbbbbc,0xba7cb927,0xb8b03a1f,0xbbffaf0e,0xa8b63bf4,
0x3bd43534,0x32a1bb91,0x39bab8d8,0xb996ba5e,0xbbffad7e,0x28b63bf8,0xb8323a3f,0x3ad03900,0x3bafb115,0xb475bbe6,0x34d5bb46,0xbba0b6aa,0xbae9364e,0x38073b5a,0xabd93bdd,0x3bfc31db,
0x3a5eb75e,0xb8d8bb1a,0xb705bbaf,0xbb303475,0xb85d39dc,0x3ab53972,0x39ba3a7c,0x3996b8b0,0x3365bb5a,0xbbc9b64e,0xbb46b887,0xb6aa3a99,0x2f0e3bfc,0x3bf42bd9,0x3bf83414,0x2d7ebbbc,
0x2bd9bbaf,0xbbfcb475,0xbbedad7e,0x304e3bf8,0x35f13be6,0x3b6eb115,0x3ab5b593,0xb85dbb80,0xb9dcba99,0xb9723887,0xb83239ba,0x3ad03996,0x3ba03807,0x34d5bae9,0x2f0ebb91,0xbbf4b534,
0xb9babae9,0xb9963807,0xb1db3b30,0x3bdd3705,0x3bc937b7,0x3365bb02,0xb593bbf8,0xbb802d7e,0xbba028b6,0x34d53bff,0x3a3f3a7c,0x3900b8b0,0x394db85d,0xb9febab5,0xbbedb64e,0xb04e3b5a,
0xbbf8b365,0x2d7e3bc9,0x3b0239dc,0x37b7b972,0x39feb64e,0xb94dbb5a,0xbbedb1db,0x304e3bdd,0xb2a13ae9,0x3bd43807,0x39bab705,0xb996bb30,0xb6aabbf4,0xbb462f0e,0xb1153b1a,0x3be6375e,
0xb8b0385d,0x3a7c3ab5,0x39dcb5f1,0xb972bb6e,0xaf0ebbbc,0xbbf4b414,0xad7e3b30,0x3bf83705,0x39fe3b1a,0x394db75e,0xb8d8bbaf,0xba5e3475,0xbc00b593,0x22483b80,0x3bdd3832,0x31dbbad0,
0x33653bdd,0x3bc931db,0xb6aabc00,0xbb462248,0xbb02ba5e,0xb7b738d8,0x3ba0394d,0x34d5b9fe,0x3b912d7e,0xb534bbf8,0xbae92f0e,0x38073bf4,0xb64e3972,0x3b5a39dc,0x32a1ba7c,0xbbd4b8b0,
0x3b1a3a7c,0x375eb8b0,0xbbf4b593,0x2f0e3b80,0xbb30a248,0x37053c00,0x3807b85d,0xbae9bab5,0x31dbba5e,0xbbddb8d8,0x364e3bfc,0x3b5a2bd9,0x39723baf,0x39dcb475,0xbbc9b927,0xb3653a1f,
0x3b6e304e,0xb5f1bbed,0xb2a139fe,0x3bd4394d,0xb1153a3f,0x3be63900,0xb9dcbba0,0xb97234d5,0xba1fbb80,0xb9273593,0x3baf3365,0xb475bbc9,0x3b9131db,0xb534bbdd,0xb41439ba,0x3bbc3996,
0x3534b900,0xbb91ba3f,0x3ae93b1a,0x3807b75e,0x39ba3bc9,0x3996b365,0xba9928b6,0x38873bff,0xbb80b2a1,0x35933bd4,0xb115bb5a,0xbbe6b64e,0x2d7eba5e,0xbbf8b8d8,0x3baf39fe,0x3475b94d,
0xb807bbf8,0xbae9ad7e,0x39feaf0e,0xb94dbbf4,0x3bdd36aa,0xb1dbbb46,0x35f13bc9,0x3b6e3365,0xb11539ba,0x3be63996,0xbbffb85d,0x28b63ab5,0xbb02bb30,0xb7b73705,0x34d5b8d8,0xbba0ba5e,
0xbbddb9fe,0xb1db394d,0xb64ebbbc,0xbb5ab414,0x36aab75e,0xbb46bb1a,0x3be637b7,0xb115bb02,0x3a3f3bc9,0x3900b365,0xad7e39dc,0x3bf83972,0xba5ea248,0x38d83c00,0xbb91bab5,0xb534385d,
0xba3fa8b6,0x39003bff,0xbbf8b8b0,0x2d7e3a7c,0xb807bbdd,0xbae9b1db,0x2bd9b9ba,0xbbfcb996,0x3b6e3534,0xb5f1bb91,0x3bd43a5e,0x32a1b8d8,0x33653b1a,0x3bc9375e,0xb59337b7,0x3b803b02,
0xa8b63996,0x3bff39ba,0xb365385d,0x3bc93ab5,0xbbf8b9fe,0xad7e394d,0xbbafbae9,0xb4753807,0x304eb900,0xbbedba3f,0x3534b75e,0xbb91bb1a,0x3bdd3a7c,0x31dbb8b0,0x3b6e3b46,0x35f1b6aa,
0x39dc3c00,0x3972a248,0x3ad03bd4,0x3832b2a1,0xb9272bd9,0x3a1f3bfc,0xb7b73414,0x3b023bbc,0xba5ebbf4,0xb8d82f0e,0xbb30bba0,0xb70534d5,0x3887b115,0xba99bbe6,0x364eb593,0xbb5abb80,
0x3bf43972,0xaf0eb9dc,0x3a1f3115,0xb927bbe6,0x34143a99,0x3bbc3887,0x39fe3c00,0x394d2248,0xbb5ab705,0x364e3b30,0xb85d304e,0x3ab53bed,0xb832bba0,0xbad0b4d5,0xbb46bbaf,0xb6aa3475,
0x3887abd9,0xba99bbfc,0xb5f1bae9,0xbb6eb807,0x3b803ba0,0x3593b4d5,0x3a7c3475,0xb8b0bbaf,0xaf0e3832,0x3bf43ad0,0x3a1f3bff,0x392728b6,0xbbedb996,0x304e39ba,0xb70532a1,0x3b303bd4,
0xb414ba1f,0xbbbcb927,0xbbfcba3f,0x2bd93900,0x3a993593,0xb887bb80,0xb64ebad0,0xbb5ab832,0x3a7c3c00,0x38b02248,0x39dc32a1,0xb972bbd4,0xb4753534,0x3baf3b91,0x3b1a3bed,0x375eb04e,
0xbb30bbf4,0xb7052f0e,0xb41434d5,0x3bbc3ba0,0x2248b832,0xbc00bad0,0xbbddb9dc,0x31db3972,0x3b46385d,0xb6aabab5,0xb8b0bb6e,0xba7cb5f1,0x3a1f3bed,0x3927304e,0x37b7abd9,0xbb02bbfc,
0xbb5ab8d8,0x364e3a5e,0x3ab53bfc,0x385d2bd9,0xba7cbbf4,0xb8b0af0e,0xa8b6375e,0x3bff3b1a,0x2d7eb6aa,0xbbf8bb46,0xbb02b832,0x37b73ad0,0x3b303887,0xb705ba99,0xbae9bc00,0xb807a248,
0xb4d53115,0x3ba03be6,0x3a3f36aa,0xb900bb46,0xbb91b996,0x353439ba,0x3bbc3bd4,0x3414b2a1,0xba99bbed,0xb887b04e,0x35f139fe,0x3b6e394d,0xa8b6b7b7,0xbbffbb02,0xb832ad7e,0x3ad03bf8,
0x38323a99,0x3ad03887,0xb593b996,0xbb80b9ba,0xb475304e,0x3baf3bed,0x375e2bd9,0xbb1abbfc,0xbb30b927,0x37053a1f,0x3bbc3a3f,0xb414b900,0xbb6ebbff,0xb5f128b6,0x3ab53be6,0x385d3115,
0x3be63bd4,0x3115b2a1,0xbbffbb5a,0x28b6364e,0x39003ae9,0x3a3f3807,0xba1fbb91,0xb927b534,0xabd934d5,0x3bfc3ba0,0xb04eb7b7,0xbbedbb02,0xb9bab6aa,0x39963b46,0x38873365,0xba99bbc9,
0x3a1f3832,0xb927bad0,0xb47528b6,0x3baf3bff,0x3bfc3b6e,0xabd9b5f1,0xba5eb887,0x38d83a99,0x3ab53bbc,0x385d3414,0xbc00bb91,0x22483534,0x35933900,0x3b803a3f,0xba7cbba0,0xb8b0b4d5,
0x2248b414,0xbc00bbbc,0x3a993b91,0x38873534,0x38323475,0xbad0bbaf,0x36aa3927,0x3b463a1f,0x3b1a39dc,0xb75eb972,0xaf0e3115,0x3bf43be6,0x3bfc3bd4,0x2bd9b2a1,0xb8d8b5f1,0x3a5e3b6e,
0xb9febb02,0xb94db7b7,0x3a5e3927,0xb8d8ba1f,0xb64eb8b0,0xbb5aba7c,0x3bd43b46,0xb2a1b6aa,0x28b6b1db,0xbbffbbdd,0x3bc93c00,0x33652248,0x375e3414,0xbb1abbbc,0x3a3f3b30,0x39003705,
0xbbedbba0,0x304e34d5,0xb534b7b7,0xbb91bb02,0xbbd4bbff,0xb2a1a8b6,0x2248b115,0xbc00bbe6,0xbad0bb6e,0xb832b5f1,0x359331db,0xbb80bbdd,0xb900b9fe,0xba3fb94d,0x39273807,0xba1fbae9,
0xb85db705,0x3ab53b30,0xbc00bbed,0x2248304e,0xb9dcb927,0x39723a1f,0xbbc9bbf4,0xb365af0e,0xbb02ba7c,0x37b738b0,0xbb1abb80,0xb75eb593,0xbbbcbb6e,0x341435f1,0xb9feba99,0xb94db887,
0x34753593,0x3baf3b80,0xb4d5b365,0x3ba03bc9,0x304e32a1,0x3bed3bd4,0xb705b5f1,0x3b303b6e,0xa2482bd9,0x3c003bfc,0xb887b807,0x3a993ae9,0xb115ad7e,0x3be63bf8,0xb972b900,0x39dc3a3f,
0x3b463b5a,0x36aa364e,0x3a7c3a99,0x38b03887,0x3b1a3b30,0x375e3705,0x3a3f3a5e,0x390038d8,0x3ae93b02,0x380737b7,0x39fe3a1f,0x394d3927,0x3ab53ad0,0x385d3832,0x39ba39dc,0x39963972,
0x28b63c00,0x3bffa248,0x33653bd4,0x3bc9b2a1,0xad7ebbfc,0xbbf82bd9,0xb475bbbc,0xbbaf3414,0x304e3bf4,0x3bedaf0e,0x35343ba0,0x3b91b4d5,0xb1dbbbe6,0xbbdd3115,0xb5f1bb80,0xbb6e3593,
0x3bf4a8b6,0xaf0ebbff,0x3a1fb8b0,0xb927ba7c,0xbbbc31db,0x34143bdd,0xb94d3996,0x39fe39ba,0x3b5ab534,0xb64ebb91,0x385dba5e,0xbab5b8d8,0xbad0375e,0x38323b1a,0xb6aa3b02,0x3b4637b7,
0xb1dbbbfc,0xbbdd2bd9,0xbb5ab807,0xb64e3ae9,0x36aa3ba0,0x3b46b4d5,0x3be63475,0x3115bbaf,0xb900bad0,0xba3f3832,0xbbf8a8b6,0x2d7e3bff,0x3a5e3996,0x38d8b9ba,0x3b91b2a1,0xb534bbd4,
0xbbbc2d7e,0x34143bf8,0x2bd93bf4,0x3bfc2f0e,0x3a99b6aa,0xb887bb46,0xb64ebbc9,0xbb5a3365,0xb8b03996,0x3a7c39ba,0x39723ab5,0x39dcb85d,0x3475bb30,0xbbafb705,0xbb1ab8d8,0xb75e3a5e,
0x35343bf4,0x3b91af0e,0x3ae9b4d5,0xb807bba0,0xb996bad0,0xb9ba3832,0xb8873972,0x3a9939dc,0x3b80385d,0x3593bab5,0x3115bb6e,0xbbe6b5f1,0xbbf8b04e,0x2d7e3bed,0x34753bfc,0x3bafabd9,
0x3b5ab04e,0xb64ebbed,0xbab5b9fe,0xb85d394d,0xb8b03900,0x3a7c3a3f,0x3bff34d5,0x28b6bba0,0x2d7ebb80,0xbbf8b593,0xbb023365,0x37b73bc9,0x37053bdd,0x3b30b1db,0x3807b996,0xbae9b9ba,
0xb75ebbe6,0xbb1a3115,0xaf0e3b46,0x3bf436aa,0x3b303996,0x3705b9ba,0xb807bbd4,0xbae932a1,0xbbddb04e,0x31db3bed,0x3b5a394d,0x364eb9fe,0x3972b7b7,0xb9dcbb02,0xbbc9ad7e,0x33653bf8,
0xbad031db,0x38323bdd,0x3b802248,0xb593bc00,0x3475ba5e,0xbbafb8d8,0xb75e394d,0x3b1a39fe,0x37053bf8,0x3b30ad7e,0xb414bbf4,0xbbbcaf0e,0xbb6eb972,0xb5f139dc,0x3ab53a7c,0x385db8b0,
0x38b03bd4,0x3a7cb2a1,0xb9dcbb5a,0xb972364e,0xbbf4b807,0xaf0e3ae9,0x3bf83534,0xad7ebb91,0x39feb4d5,0xb94dbba0,0xb8d837b7,0x3a5e3b02,0xa2483b46,0x3c0036aa,0xb1dbbbc9,0xbbddb365,
0x3a1fb365,0xb927bbc9,0xb47539dc,0x3baf3972,0x2bd93b5a,0x3bfc364e,0xb8d8bbdd,0xba5e31db,0xbab5bae9,0xb85d3807,0x3c003705,0xa248bb30,0x3b802f0e,0xb593bbf4,0xb8b0375e,0x3a7c3b1a,
0xb996bbbc,0xb9ba3414,0x3bdd3534,0xb1dbbb91,0x3bc93475,0xb365bbaf,0xb5933927,0x3b803a1f,0xb4d53972,0x3ba039dc,0xb900bbe6,0xba3f3115,0xb94dbbd4,0xb9fe32a1,0x3bed35f1,0xb04ebb6e,
0xb94d3475,0x39fe3baf,0xb8d8bbf8,0xba5e2d7e,0xb64ebbe6,0xbb5ab115,0x3bd43593,0xb2a1bb80,0x3bff3887,0x28b6ba99,0xb3653996,0x3bc939ba,0xb75e3807,0x3b1a3ae9,0xba3fbb91,0xb9003534,
0x3a5e3ba0,0x38d8b4d5,0xb70537b7,0x3b303b02,0xbab5a8b6,0x385d3bff,0xb996bbe6,0xb9ba3115,0xb365bb6e,0xbbc9b5f1,0x3b4631db,0xb6aabbdd,0x3bf4394d,0x2f0eb9fe,0x2d7e3ae9,0x3bf83807,
0x385db534,0xbab5bb91,0x3c0038d8,0xa248ba5e,0x39723bf8,0x39dcad7e,0xb3653900,0x3bc93a3f,0xbb02b115,0x37b73be6,0xbb1abb46,0xb75e36aa,0xb414bb5a,0xbbbcb64e,0x394db1db,0xb9febbdd,
0xbb02bb80,0xb7b73593,0xb75ebbc9,0xbb1ab365,0x38d8b2a1,0xba5ebbd4,0x3b9135f1,0xb534bb6e,0x39963bfc,0x39baabd9,0x31db3ae9,0x3bdd3807,0xba7cad7e,0x38b03bf8,0xbbffb900,0x28b63a3f,
0xb6aa35f1,0x3b463b6e,0xb8b031db,0x3a7c3bdd,0xbb1abb91,0xb75e3534,0xba3fbbed,0xb900304e,0x3807b475,0xbae9bbaf,0x394dad7e,0xb9febbf8,0x3ab53bc9,0x385db365,0x39ba3bff,0x3996a8b6,
0x3b803b5a,0x3593b64e,0x3be63a99,0x3115b887,0xb4d53705,0x3ba03b30,0xaf0e38d8,0x3bf43a5e,0xbbbcbb02,0xb41437b7,0xbbfcba1f,0xabd93927,0x32a1b832,0xbbd4bad0,0x2248b972,0xbc00b9dc,
0x3475b6aa,0xbbafbb46,0xb4d5bad0,0xbba0b832,0x3bed3ab5,0x304eb85d,0x3b30364e,0xb705bb5a,0x2248394d,0x3c0039fe,0x38873bbc,0x3a993414,0xbbe6b927,0x31153a1f,0xb9dcaf0e,0x39723bf4,
0xbbd4bb30,0xb2a13705,0xb9bab04e,0x39963bed,0xa8b6b927,0xbbffba1f,0xbad0bbf4,0xb8322f0e,0x3baf38b0,0xb475ba7c,0x34d5b593,0xbba0bb80,0x38073b6e,0x3ae935f1,0x3bfc3a99,0x2bd9b887,
0xb04e375e,0x3bed3b1a,0x3b913baf,0x3534b475,0xbbd4b972,0x32a139dc,0x224838b0,0x3c003a7c,0xb832bb5a,0xbad0b64e,0xbb80b887,0x35933a99,0x39002bd9,0xba3fbbfc,0xb927bbbc,0xba1fb414,
0x3bfc3b02,0x2bd9b7b7,0xb04eb927,0xbbedba1f,0x35f13a7c,0x3b6e38b0,0x3ab536aa,0xb85dbb46,0xb972b1db,0x39dc3bdd,0x3ad03c00,0x3832a248,0xbba0bbbc,0xb4d53414,0xaf0e3705,0x3bf43b30,
0xa248b807,0xbc00bae9,0xba99b705,0x38873b30,0x3ad037b7,0xb832bb02,0xbb46bbf8,0xb6aa2d7e,0x3b1a3bff,0x375ea8b6,0xaf0eb8b0,0xbbf4ba7c,0x2bd9385d,0x3bfc3ab5,0x3a5e364e,0xb8d8bb5a,
0xbbf8bad0,0x2d7e3832,0x3b023bff,0x37b728b6,0xb94dbb6e,0xb9feb5f1,0x304e3887,0x3bed3a99,0x32a1b414,0xbbd4bbbc,0xb9bab534,0x39963b91,0x3b463900,0xb6aaba3f,0xbbe6bba0,0xb11534d5,
0x3115385d,0x3be63ab5,0x28b6b5f1,0xbbffbb6e,0xb900b414,0x3a3f3bbc,0x3a1f3705,0xb927bb30,0xbbfcbb1a,0x2bd9375e,0x3bed3baf,0x304eb475,0xb9babb80,0xb996b593,0x38873ad0,0x3a993832,
0x3bc93a99,0xb365b887,0xbb46b996,0x36aa39ba,0x3b023bed,0x37b7304e,0xbba0bbfc,0xb4d52bd9,0x35343927,0x3b913a1f,0xb807ba3f,0xbae9b900,0xb64ea8b6,0x3b5a3bff,0x32a1b115,0xbbd4bbe6,
0xb4d5b8b0,0xbba0ba7c,0x3a3f3b80,0x39003593,0x35342248,0xbb91bc00,0x3414385d,0x3bbc3ab5,0x3a9938d8,0xb887ba5e,0xb5f1abd9,0x3b6e3bfc,0x3bff3baf,0x28b6b475,0xbad0b927,0x38323a1f,
0xbb6eba5e,0x35f138d8,0x32a1abd9,0xbbd4bbfc,0xbbe6bbf4,0xb1152f0e,0x3972375e,0xb9dcbb1a,0xba1fbb46,0xb927b6aa,0x3baf3ad0,0xb475b832,0xb534b887,0xbb91ba99,0x3bbc3c00,0x3414a248,
0x37053900,0x3b303a3f,0xbbbcbb1a,0x3414375e,0x22483365,0x3c003bc9,0xbbddbbff,0xb1db28b6,0xb6aab2a1,0x3b463bd4,0xba7cbb5a,0xb8b0b64e,0xba1fb8d8,0x39273a5e,0xb7b7b94d,0xbb02b9fe,
0x3ae93a1f,0xb807b927,0x394d3a3f,0x39fe3900,0x3bdd3b80,0xb1dbb593,0x35f13832,0x3b6e3ad0,0x3be63c00,0x3115a248,0x28b632a1,0x3bff3bd4,0x3b023b91,0x37b73534,0xb4d5b04e,0x3ba03bed,
0xb887b94d,0xba99b9fe,0x35f13414,0xbb6ebbbc,0xb593b75e,0xbb80bb1a,0x38b037b7,0xba7cbb02,0xaf0eb365,0xbbf4bbc9,0x3a1f3972,0xb927b9dc,0x304e2248,0xbbedbc00,0x3b303ab5,0xb705b85d,
0xba3fb9dc,0x39003972,0xbbf8bbe6,0x2d7e3115,0xbae9ba99,0x38073887,0xbbfcbc00,0xabd92248,0xbb6ebb30,0x35f13705,0xbbd4bbed,0xb2a1b04e,0xbbc9bba0,0x336534d5,0xbb80bbaf,0xb593b475,
0x39723996,0x39dc39ba,0x3832385d,0x3ad03ab5,0x3927394d,0x3a1f39fe,0x37b73807,0x3b023ae9,0x38d83900,0x3a5e3a3f,0x3705375e,0x3b303b1a,0x388738b0,0x3a993a7c,0x364e36aa,0x3b5a3b46,
0x36aa3b5a,0x3b46b64e,0x38b03a99,0x3a7cb887,0xb75ebb30,0xbb1a3705,0xb900ba5e,0xba3f38d8,0x38073b02,0x3ae9b7b7,0x394d3a1f,0x39feb927,0xb85dbad0,0xbab53832,0xb996b9dc,0xb9ba3972,
0x3475bb80,0xbbafb593,0xb4d5bbc9,0xbba03365,0xb04e3bd4,0x3bed32a1,0x37053b6e,0x3b30b5f1,0xa248bbfc,0xbc00abd9,0xb887bae9,0xba993807,0x31153bf8,0x3be6ad7e,0x39723a3f,0x39dcb900,
0xbab53705,0x385d3b30,0xa2483bed,0x3c00304e,0x3972b927,0xb9dcba1f,0xb365bbf4,0xbbc92f0e,0xb7b73a7c,0x3b0238b0,0x375e3b80,0x3b1ab593,0x3414bb6e,0xbbbcb5f1,0xb94dba99,0xb9fe3887,
0x3bed34d5,0x304ebba0,0x3534bb02,0xbb91b7b7,0xbbd428b6,0x32a13bff,0x22483be6,0x3c003115,0x3ad0b5f1,0xb832bb6e,0xb593bbdd,0xbb8031db,0xb900394d,0x3a3f39fe,0x39273ae9,0x3a1fb807,
0xb94dbb02,0xb9fe37b7,0xb8d83927,0x3a5e3a1f,0x3b5a38b0,0x364eba7c,0x32a1bb46,0xbbd4b6aa,0xbbffb1db,0x28b63bdd,0x33653c00,0x3bc9a248,0x3b1ab414,0xb75ebbbc,0xb900bb30,0xba3f3705,
0x22483bbc,0x3c003414,0x3a99b534,0xb887bb91,0xb832bbaf,0xbad03475,0xb6aa3a1f,0x3b463927,0x3b1a3972,0x375eb9dc,0xaf0ebbe6,0xbbf4b115,0xbbfcb2a1,0x2bd93bd4,0x38d83b6e,0x3a5eb5f1,
0x3927b832,0xba1fbad0,0xbbafa8b6,0x34753bff,0xabd93b6e,0x3bfc35f1,0x38d8b887,0xba5eba99,0xb85dbbbc,0xbab53414,0xa2483b91,0x3c003534,0x3b803900,0x3593ba3f,0xb8b0bba0,0xba7c34d5,
0xbbe6b2a1,0x31153bd4,0x3bff364e,0x28b6bb5a,0x3900b807,0xba3fbae9,0xba1f3534,0x39273b91,0x2bd93ba0,0x3bfc34d5,0x304ebb02,0xbbedb7b7,0xb9babb46,0xb99636aa,0x38873bc9,0x3a99b365,
0x3ad03a99,0x3832b887,0xbb80b996,0xb59339ba,0xbbafb04e,0x34753bed,0x3b1aabd9,0xb75ebbfc,0x3705b927,0xbb30ba1f,0xb4143a3f,0x3bbc3900,0x35f13bff,0x3b6e28b6,0xb85dbbe6,0xbab53115,
0xb4d5bbe6,0xbba0b115,0x3a3f3b46,0x3900b6aa,0x3b9139ba,0x3534b996,0xbbbcb2a1,0x34143bd4,0xba99304e,0x38873bed,0x35f1b94d,0xbb6eb9fe,0x28b6bb02,0xbbffb7b7,0x38323bf8,0x3ad0ad7e,
0xb64e38d8,0x3b5a3a5e,0xb85dbbfc,0xbab52bd9,0xb8b0bbf4,0xba7c2f0e,0x3bff375e,0xa8b6bb1a,0x3bf836aa,0xad7ebb46,0xb7b73832,0x3b023ad0,0xb7053887,0x3b303a99,0xb807bc00,0xbae92248,
0x3b302f0e,0xb705bbf4,0x34143ba0,0x3bbc34d5,0x22483ad0,0x3c003832,0xbbddb972,0xb1db39dc,0xbb46bab5,0xb6aa385d,0x38b0b5f1,0xba7cbb6e,0x3a1fb04e,0xb927bbed,0x37b73bfc,0x3b022bd9,
0xbbbcba1f,0xb4143927,0x2bd9ba3f,0xbbfcb900,0x3887b593,0xba99bb80,0x3b5a3ad0,0x364eb832,0x38b03c00,0x3a7ca248,0xb97232a1,0x39dc3bd4,0xbbafb534,0x34753b91,0xb75ebbed,0xbb1ab04e,
0x38873bfc,0x3a992bd9,0xb5f13807,0x3b6e3ae9,0xbb80b4d5,0x35933ba0,0xba7cbbaf,0xb8b03475,0xaf0ebad0,0xbbf4b832,0x3a1fa8b6,0xb927bbff,0x3bed39ba,0x304eb996,0x37053bd4,0x3b3032a1,
0x2f0eb972,0xbbf4b9dc,0x3927b115,0xba1fbbe6,0x3bbc3a99,0x3414b887,0x394d3c00,0x39fea248,0xb64e3705,0x3b5a3b30,0xbab5b04e,0x385d3bed,0xbad0bba0,0xb83234d5,0xb6aabbaf,0xbb46b475,
0xb9dca248,0x39723c00,0xbad0b2a1,0x38323bd4,0xb927bbfc,0xba1fabd9,0xb7b7bbbc,0xbb02b414,0x3a5e2f0e,0xb8d8bbf4,0x3b3034d5,0xb705bba0,0x38873be6,0x3a993115,0x364e3b80,0x3b5a3593,
0x3bff3996,0xa8b6b9ba,0x3bc9385d,0xb365bab5,0x2d7e39fe,0x3bf8394d,0x34753ae9,0x3baf3807,0xbbedb900,0x304e3a3f,0xbb91b75e,0x35343b1a,0xb1dbba7c,0xbbddb8b0,0xb5f1bb46,0xbb6eb6aa,
0xba3fbbff,0xb90028b6,0xbbf8ba7c,0xad7e38b0,0x3807b1db,0xbae9bbdd,0xabd9b996,0xbbfcb9ba,0x3b6e3b91,0x35f1b534,0x3bd438d8,0xb2a1ba5e,0xb365375e,0x3bc93b1a,0x35933b02,0x3b8037b7,
0x31db39fe,0x3bdd394d,0x3b5a3bbc,0x364eb414,0xbb46b75e,0x36aa3b1a,0xb11537b7,0x3be63b02,0xb900bbc9,0xba3fb365,0xbbf8b9dc,0x2d7e3972,0x38d8a248,0xba5ebc00,0xb534bab5,0xbb91b85d,
0x3807ad7e,0xbae9bbf8,0xb9febbf4,0xb94daf0e,0x3bdd3b46,0x31dbb6aa,0x35f1b365,0xbb6ebbc9,0x31153996,0x3be639ba,0x3bff3ab5,0x28b6b85d,0xbb02b705,0x37b73b30,0x34d53a5e,0x3ba038d8,
0xbb91b900,0x35343a3f,0x38073b1a,0x3ae9375e,0xb996bbc9,0xb9bab365,0xb887a8b6,0x3a993bff,0x3593b2a1,0xbb80bbd4,0xbbe6bb5a,0xb115364e,0x3bf83a5e,0xad7eb8d8,0xb475b9fe,0xbbafb94d,
0x3b6e3bed,0x35f1b04e,0xb2a1b94d,0xbbd4b9fe,0x31153900,0x3be63a3f,0x39dc34d5,0xb972bba0,0xba1fb593,0x39273b80,0x3baf3bc9,0x3475b365,0xbb91bbdd,0xb53431db,0x34143996,0x3bbc39ba,
0xb75eba7c,0xbb1ab8b0,0xaf0e3593,0x3bf43b80,0x3705a248,0xbb30bc00,0xbae9b85d,0x38073ab5,0x3bdd3a5e,0xb1dbb8d8,0xbb5abbfc,0xb64e2bd9,0x39dc3baf,0x39723475,0xb365b927,0xbbc9ba1f,
0xb36531db,0x3bc93bdd,0x36aa2248,0xbb46bc00,0xbb02b8d8,0x37b73a5e,0x3ba039fe,0xb4d5b94d,0xbb91bbf8,0xb5342d7e,0x3ae93bf4,0x38072f0e,0xb64eb9dc,0xbb5ab972,0x32a138b0,0x3bd43a7c,
0x3a7c385d,0xb8b0bab5,0xb972b5f1,0x39dc3b6e,0x3bf43bbc,0x2f0eb414,0xbbf8bb30,0x2d7e3705,0x394d3b1a,0x39fe375e,0xba5ebbaf,0xb8d8b475,0xa2483593,0x3c003b80,0xb1dbb832,0xbbddbad0,
0xbbf8bbc9,0xad7e3365,0x3b023972,0xb7b7b9dc,0xb9febb5a,0xb94db64e,0x3bed3bdd,0x304eb1db,0xb2a1b807,0xbbd4bae9,0x39ba3b30,0x39963705,0x36aa2f0e,0xbb46bbf4,0x3115375e,0x3be63b1a,
0x39963ae9,0x39ba3807,0xbbddbb30,0x31db3705,0x336537b7,0x3bc93b02,0xbb80bbf8,0xb593ad7e,0xb4d5a8b6,0x3ba03bff,0xb900ba7c,0xba3fb8b0,0xb9feb85d,0x394d3ab5,0xb04eb64e,0xbbedbb5a,
0xabd9b475,0xbbfcbbaf,0x3bed3bf8,0x304ead7e,0x35f13115,0xbb6ebbe6,0x3ab53b80,0x385d3593,0x39dc3887,0xb972ba99,0x38323996,0x3ad039ba,0x3ba03ae9,0xb4d5b807,0x2f0e3534,0x3bf43b91,
0xb8d8b75e,0x3a5e3b1a,0xbb30bbaf,0xb705b475,0xbab5b9dc,0x385d3972,0xb996ba7c,0xb9bab8b0,0xbbc9bb5a,0x3365364e,0xb6aab887,0xbb46ba99,0xbbf4bbfc,0xaf0e2bd9,0xad7eb414,0xbbf8bbbc,
0x3bd43b91,0xb2a1b534,0x39ba3a5e,0x399638d8,0x3bff3bf8,0x28b6ad7e,0x38323900,0x3ad03a3f,0x3baf3be6,0x34753115,0x34d536aa,0x3ba03b46,0x3ae93b5a,0x3807364e,0x2bd931db,0x3bfc3bdd,
0xbb02bb46,0xb7b7b6aa,0xb75eb832,0xbb1abad0,0xba5ebab5,0xb8d8b85d,0xb534b64e,0xbb91bb5a,0xb996b9fe,0xb9bab94d,0xb1dbb414,0xbbddbbbc,0xb8b0b927,0xba7cba1f,0xa8b6af0e,0xbbffbbf4,
0x359335f1,0x3b803b6e,0x311531db,0x3be63bdd,0x34d53534,0x3ba03b91,0x2f0e304e,0x3bf43bed,0x34143475,0x3bbc3baf,0x2bd92d7e,0x3bfc3bf8,0x32a13365,0x3bd43bc9,0x224828b6,0x3c003bff,
0x40000,0x60002,0xc0008,0xe000a,0x380034,0x3a0036,0x40003c,0x42003e,0x6c0068,0x6e006a,0x740070,0x760072,0xa0009c,0xa2009e,0xa800a4,0xaa00a6,
0xd400d0,0xd600d2,0xdc00d8,0xde00da,0x1080104,0x10a0106,0x110010c,0x112010e,0x13c0138,0x13e013a,0x1440140,0x1460142,0x170016c,0x172016e,0x1780174,0x17a0176,
0x1a401a0,0x1a601a2,0x1ac01a8,0x1ae01aa,0x1d801d4,0x1da01d6,0x1e001dc,0x1e201de,0x20c0208,0x20e020a,0x2140210,0x2160212,0x240023c,0x242023e,0x2480244,0x24a0246,
0x2740270,0x2760272,0x27c0278,0x27e027a,0x2a802a4,0x2aa02a6,0x2b002ac,0x2b202ae,0x2dc02d8,0x2de02da,0x2e402e0,0x2e602e2,0x310030c,0x312030e,0x3180314,0x31a0316,
0x3440340,0x3460342,0x34c0348,0x34e034a,0x3780374,0x37a0376,0x380037c,0x382037e,0x3ac03a8,0x3ae03aa,0x3b403b0,0x3b603b2,0x3e003dc,0x3e203de,0x3e803e4,0x3ea03e6,
0x4140410,0x4160412,0x41c0418,0x41e041a,0x4480444,0x44a0446,0x450044c,0x452044e,0x47c0478,0x47e047a,0x4840480,0x4860482,0x4b004ac,0x4b204ae,0x4b804b4,0x4ba04b6,
0x4e404e0,0x4e604e2,0x4ec04e8,0x4ee04ea,0x5180514,0x51a0516,0x520051c,0x522051e,0x54c0548,0x54e054a,0x5540550,0x5560552,0x580057c,0x582057e,0x5880584,0x58a0586,
0x5b405b0,0x5b605b2,0x5bc05b8,0x5be05ba,0x5e805e4,0x5ea05e6,0x5f005ec,0x5f205ee,0x61c0618,0x61e061a,0x6240620,0x6260622,0x650064c,0x652064e,0x6580654,0x65a0656,
0x140010,0x160012,0x120010,0x440012,0x480044,0x4a0046,0x460044,0x780046,0x7c0078,0x7e007a,0x7a0078,0xac007a,0xb000ac,0xb200ae,0xae00ac,0xe000ae,
0xe400e0,0xe600e2,0xe200e0,0x11400e2,0x1180114,0x11a0116,0x1160114,0x1480116,0x14c0148,0x14e014a,0x14a0148,0x17c014a,0x180017c,0x182017e,0x17e017c,0x1b0017e,
0x1b401b0,0x1b601b2,0x1b201b0,0x1e401b2,0x1e801e4,0x1ea01e6,0x1e601e4,0x21801e6,0x21c0218,0x21e021a,0x21a0218,0x24c021a,0x250024c,0x252024e,0x24e024c,0x280024e,
0x2840280,0x2860282,0x2820280,0x2b40282,0x2b802b4,0x2ba02b6,0x2b602b4,0x2e802b6,0x2ec02e8,0x2ee02ea,0x2ea02e8,0x31c02ea,0x320031c,0x322031e,0x31e031c,0x350031e,
0x3540350,0x3560352,0x3520350,0x3840352,0x3880384,0x38a0386,0x3860384,0x3b80386,0x3bc03b8,0x3be03ba,0x3ba03b8,0x3ec03ba,0x3f003ec,0x3f203ee,0x3ee03ec,0x42003ee,
0x4240420,0x4260422,0x4220420,0x4540422,0x4580454,0x45a0456,0x4560454,0x4880456,0x48c0488,0x48e048a,0x48a0488,0x4bc048a,0x4c004bc,0x4c204be,0x4be04bc,0x4f004be,
0x4f404f0,0x4f604f2,0x4f204f0,0x52404f2,0x5280524,0x52a0526,0x5260524,0x5580526,0x55c0558,0x55e055a,0x55a0558,0x58c055a,0x590058c,0x592058e,0x58e058c,0x5c0058e,
0x5c405c0,0x5c605c2,0x5c205c0,0x5f405c2,0x5f805f4,0x5fa05f6,0x5f605f4,0x62805f6,0x62c0628,0x62e062a,0x62a0628,0x65c062a,0x660065c,0x662065e,0x65e065c,0x18065e,
0x180018,0x4c001a,0x1a0018,0x4c001a,0x4c004c,0x80004e,0x4e004c,0x80004e,0x800080,0xb40082,0x820080,0xb40082,0xb400b4,0xe800b6,0xb600b4,0xe800b6,
0xe800e8,0x11c00ea,0xea00e8,0x11c00ea,0x11c011c,0x150011e,0x11e011c,0x150011e,0x1500150,0x1840152,0x1520150,0x1840152,0x1840184,0x1b80186,0x1860184,0x1b80186,
0x1b801b8,0x1ec01ba,0x1ba01b8,0x1ec01ba,0x1ec01ec,0x22001ee,0x1ee01ec,0x22001ee,0x2200220,0x2540222,0x2220220,0x2540222,0x2540254,0x2880256,0x2560254,0x2880256,
0x2880288,0x2bc028a,0x28a0288,0x2bc028a,0x2bc02bc,0x2f002be,0x2be02bc,0x2f002be,0x2f002f0,0x32402f2,0x2f202f0,0x32402f2,0x3240324,0x3580326,0x3260324,0x3580326,
0x3580358,0x38c035a,0x35a0358,0x38c035a,0x38c038c,0x3c0038e,0x38e038c,0x3c0038e,0x3c003c0,0x3f403c2,0x3c203c0,0x3f403c2,0x3f403f4,0x42803f6,0x3f603f4,0x42803f6,
0x4280428,0x45c042a,0x42a0428,0x45c042a,0x45c045c,0x490045e,0x45e045c,0x490045e,0x4900490,0x4c40492,0x4920490,0x4c40492,0x4c404c4,0x4f804c6,0x4c604c4,0x4f804c6,
0x4f804f8,0x52c04fa,0x4fa04f8,0x52c04fa,0x52c052c,0x560052e,0x52e052c,0x560052e,0x5600560,0x5940562,0x5620560,0x5940562,0x5940594,0x5c80596,0x5960594,0x5c80596,
0x5c805c8,0x5fc05ca,0x5ca05c8,0x5fc05ca,0x5fc05fc,0x63005fe,0x5fe05fc,0x63005fe,0x6300630,0x6640632,0x6320630,0x6640632,0x6640664,0x1c0666,0x6660664,0x1c0666,
0x1c001c,0x50001e,0x1e001c,0x50001e,0x500050,0x840052,0x520050,0x840052,0x840084,0xb80086,0x860084,0xb80086,0xb800b8,0xec00ba,0xba00b8,0xec00ba,
0xec00ec,0x12000ee,0xee00ec,0x12000ee,0x1200120,0x1540122,0x1220120,0x1540122,0x1540154,0x1880156,0x1560154,0x1880156,0x1880188,0x1bc018a,0x18a0188,0x1bc018a,
0x1bc01bc,0x1f001be,0x1be01bc,0x1f001be,0x1f001f0,0x22401f2,0x1f201f0,0x22401f2,0x2240224,0x2580226,0x2260224,0x2580226,0x2580258,0x28c025a,0x25a0258,0x28c025a,
0x28c028c,0x2c0028e,0x28e028c,0x2c0028e,0x2c002c0,0x2f402c2,0x2c202c0,0x2f402c2,0x2f402f4,0x32802f6,0x2f602f4,0x32802f6,0x3280328,0x35c032a,0x32a0328,0x35c032a,
0x35c035c,0x390035e,0x35e035c,0x390035e,0x3900390,0x3c40392,0x3920390,0x3c40392,0x3c403c4,0x3f803c6,0x3c603c4,0x3f803c6,0x3f803f8,0x42c03fa,0x3fa03f8,0x42c03fa,
0x42c042c,0x460042e,0x42e042c,0x460042e,0x4600460,0x4940462,0x4620460,0x4940462,0x4940494,0x4c80496,0x4960494,0x4c80496,0x4c804c8,0x4fc04ca,0x4ca04c8,0x4fc04ca,
0x4fc04fc,0x53004fe,0x4fe04fc,0x53004fe,0x5300530,0x5640532,0x5320530,0x5640532,0x5640564,0x5980566,0x5660564,0x5980566,0x5980598,0x5cc059a,0x59a0598,0x5cc059a,
0x5cc05cc,0x60005ce,0x5ce05cc,0x60005ce,0x6000600,0x6340602,0x6020600,0x6340602,0x6340634,0x6680636,0x6360634,0x6680636,0x6680668,0x20066a,0x66a0668,0x20066a,
0x5d605d6,0x60a05d6,0x5d605d6,0x60a060a,0x60a060a,0x63e063e,0x60a060a,0x63e063e,0x63e063e,0x672063e,0x63e063e,0x6720672,0x6720672,0x280028,0x6720672,0x280028,
0x5060506,0x53a0506,0x5060506,0x53a053a,0x53a053a,0x56e056e,0x53a053a,0x56e056e,0x56e056e,0x5a2056e,0x56e056e,0x5a205a2,0x5a205a2,0x5d605d6,0x5a205a2,0x5d605d6,
0x4360436,0x46a0436,0x4360436,0x46a046a,0x46a046a,0x49e049e,0x46a046a,0x49e049e,0x49e049e,0x4d2049e,0x49e049e,0x4d204d2,0x4d204d2,0x5060506,0x4d204d2,0x5060506,
0x3660366,0x39a0366,0x3660366,0x39a039a,0x39a039a,0x3ce03ce,0x39a039a,0x3ce03ce,0x3ce03ce,0x40203ce,0x3ce03ce,0x4020402,0x4020402,0x4360436,0x4020402,0x4360436,
0x2960296,0x2ca0296,0x2960296,0x2ca02ca,0x2ca02ca,0x2fe02fe,0x2ca02ca,0x2fe02fe,0x2fe02fe,0x33202fe,0x2fe02fe,0x3320332,0x3320332,0x3660366,0x3320332,0x3660366,
0x1c601c6,0x1fa01c6,0x1c601c6,0x1fa01fa,0x1fa01fa,0x22e022e,0x1fa01fa,0x22e022e,0x22e022e,0x262022e,0x22e022e,0x2620262,0x2620262,0x2960296,0x2620262,0x2960296,
0xf600f6,0x12a00f6,0xf600f6,0x12a012a,0x12a012a,0x15e015e,0x12a012a,0x15e015e,0x15e015e,0x192015e,0x15e015e,0x1920192,0x1920192,0x1c601c6,0x1920192,0x1c601c6,
0x260026,0x5a0026,0x260026,0x5a005a,0x5a005a,0x8e008e,0x5a005a,0x8e008e,0x8e008e,0xc2008e,0x8e008e,0xc200c2,0xc200c2,0xf600f6,0xc200c2,0xf600f6,
0x5d405d4,0x60805d4,0x5d405d4,0x6080608,0x6080608,0x63c063c,0x6080608,0x63c063c,0x63c063c,0x670063c,0x63c063c,0x6700670,0x6700670,0x260026,0x6700670,0x260026,
0x5040504,0x5380504,0x5040504,0x5380538,0x5380538,0x56c056c,0x5380538,0x56c056c,0x56c056c,0x5a0056c,0x56c056c,0x5a005a0,0x5a005a0,0x5d405d4,0x5a005a0,0x5d405d4,
0x4340434,0x4680434,0x4340434,0x4680468,0x4680468,0x49c049c,0x4680468,0x49c049c,0x49c049c,0x4d0049c,0x49c049c,0x4d004d0,0x4d004d0,0x5040504,0x4d004d0,0x5040504,
0x3640364,0x3980364,0x3640364,0x3980398,0x3980398,0x3cc03cc,0x3980398,0x3cc03cc,0x3cc03cc,0x40003cc,0x3cc03cc,0x4000400,0x4000400,0x4340434,0x4000400,0x4340434,
0x2940294,0x2c80294,0x2940294,0x2c802c8,0x2c802c8,0x2fc02fc,0x2c802c8,0x2fc02fc,0x2fc02fc,0x33002fc,0x2fc02fc,0x3300330,0x3300330,0x3640364,0x3300330,0x3640364,
0x1c401c4,0x1f801c4,0x1c401c4,0x1f801f8,0x1f801f8,0x22c022c,0x1f801f8,0x22c022c,0x22c022c,0x260022c,0x22c022c,0x2600260,0x2600260,0x2940294,0x2600260,0x2940294,
0xf400f4,0x12800f4,0xf400f4,0x1280128,0x1280128,0x15c015c,0x1280128,0x15c015c,0x15c015c,0x190015c,0x15c015c,0x1900190,0x1900190,0x1c401c4,0x1900190,0x1c401c4,
0x240024,0x580024,0x240024,0x580058,0x580058,0x8c008c,0x580058,0x8c008c,0x8c008c,0xc0008c,0x8c008c,0xc000c0,0xc000c0,0xf400f4,0xc000c0,0xf400f4,
0x5d205d2,0x60605d2,0x5d205d2,0x6060606,0x6060606,0x63a063a,0x6060606,0x63a063a,0x63a063a,0x66e063a,0x63a063a,0x66e066e,0x66e066e,0x240024,0x66e066e,0x240024,
0x5020502,0x5360502,0x5020502,0x5360536,0x5360536,0x56a056a,0x5360536,0x56a056a,0x56a056a,0x59e056a,0x56a056a,0x59e059e,0x59e059e,0x5d205d2,0x59e059e,0x5d205d2,
0x4320432,0x4660432,0x4320432,0x4660466,0x4660466,0x49a049a,0x4660466,0x49a049a,0x49a049a,0x4ce049a,0x49a049a,0x4ce04ce,0x4ce04ce,0x5020502,0x4ce04ce,0x5020502,
0x3620362,0x3960362,0x3620362,0x3960396,0x3960396,0x3ca03ca,0x3960396,0x3ca03ca,0x3ca03ca,0x3fe03ca,0x3ca03ca,0x3fe03fe,0x3fe03fe,0x4320432,0x3fe03fe,0x4320432,
0x2920292,0x2c60292,0x2920292,0x2c602c6,0x2c602c6,0x2fa02fa,0x2c602c6,0x2fa02fa,0x2fa02fa,0x32e02fa,0x2fa02fa,0x32e032e,0x32e032e,0x3620362,0x32e032e,0x3620362,
0x1c201c2,0x1f601c2,0x1c201c2,0x1f601f6,0x1f601f6,0x22a022a,0x1f601f6,0x22a022a,0x22a022a,0x25e022a,0x22a022a,0x25e025e,0x25e025e,0x2920292,0x25e025e,0x2920292,
0xf200f2,0x12600f2,0xf200f2,0x1260126,0x1260126,0x15a015a,0x1260126,0x15a015a,0x15a015a,0x18e015a,0x15a015a,0x18e018e,0x18e018e,0x1c201c2,0x18e018e,0x1c201c2,
0x220022,0x560022,0x220022,0x560056,0x560056,0x8a008a,0x560056,0x8a008a,0x8a008a,0xbe008a,0x8a008a,0xbe00be,0xbe00be,0xf200f2,0xbe00be,0xf200f2,
0x5d005d0,0x60405d0,0x5d005d0,0x6040604,0x6040604,0x6380638,0x6040604,0x6380638,0x6380638,0x66c0638,0x6380638,0x66c066c,0x66c066c,0x220022,0x66c066c,0x220022,
0x5000500,0x5340500,0x5000500,0x5340534,0x5340534,0x5680568,0x5340534,0x5680568,0x5680568,0x59c0568,0x5680568,0x59c059c,0x59c059c,0x5d005d0,0x59c059c,0x5d005d0,
0x4300430,0x4640430,0x4300430,0x4640464,0x4640464,0x4980498,0x4640464,0x4980498,0x4980498,0x4cc0498,0x4980498,0x4cc04cc,0x4cc04cc,0x5000500,0x4cc04cc,0x5000500,
0x3600360,0x3940360,0x3600360,0x3940394,0x3940394,0x3c803c8,0x3940394,0x3c803c8,0x3c803c8,0x3fc03c8,0x3c803c8,0x3fc03fc,0x3fc03fc,0x4300430,0x3fc03fc,0x4300430,
0x2900290,0x2c40290,0x2900290,0x2c402c4,0x2c402c4,0x2f802f8,0x2c402c4,0x2f802f8,0x2f802f8,0x32c02f8,0x2f802f8,0x32c032c,0x32c032c,0x3600360,0x32c032c,0x3600360,
0x1c001c0,0x1f401c0,0x1c001c0,0x1f401f4,0x1f401f4,0x2280228,0x1f401f4,0x2280228,0x2280228,0x25c0228,0x2280228,0x25c025c,0x25c025c,0x2900290,0x25c025c,0x2900290,
0xf000f0,0x12400f0,0xf000f0,0x1240124,0x1240124,0x1580158,0x1240124,0x1580158,0x1580158,0x18c0158,0x1580158,0x18c018c,0x18c018c,0x1c001c0,0x18c018c,0x1c001c0,
0x200020,0x540020,0x200020,0x540054,0x540054,0x880088,0x540054,0x880088,0x880088,0xbc0088,0x880088,0xbc00bc,0xbc00bc,0xf000f0,0xbc00bc,0xf000f0,
0x30003000,0x30003000,0x30003000,0x30003000,0x30003000,0x30003000,0x30003000,0x30003000,0x0,0x0,0x0,0x0,0x0,0x0,0x0,0x0,
0x30003000,0x30003000,0x30003000,0x30003000,0x30003000,0x30003000,0x30003000,0x30003000,0x0,0x0,0x0,0x0,0x0,0x0,0x0,0x0,
0x2a1f2da8,0xaf64ada8,0xaa1fada8,0x2f642da8,0x2f643000,0xaa1f0000,0xaf64b000,0x2a1f8000,0x2f642da8,0x2a1f2da8,0xaf64ada8,0xaa1fada8,0x2a1f0000,0x2f643000,0xaa1f0000,0xaf64b000,
0x263e2c72,0xafd9aea7,0xa63eac72,0x2fd92ea7,0x2ea72fd9,0xac72a63e,0xaea7afd9,0x2c72263e,0x2fd92ea7,0x263e2c72,0xafd9aea7,0xa63eac72,0x2c72263e,0x2ea72fd9,0xac72a63e,0xaea7afd9,
0x2da80000,0xada80000,0x2da88000,0xada80000,0x2da83000,0xada8b000,0x2da83000,0xada8b000,0x2da83000,0xada8b000,0x2da83000,0xada8b000,0xada80000,0x2da88000,0xada80000,0x2da88000,
0x2f642a1f,0xaf64aa1f,0x2f642a1f,0xaf64aa1f,0x2a1f2f64,0xaa1faf64,0x2a1f2f64,0xaa1faf64,0x2a1f2f64,0xaa1faf64,0x2a1f2f64,0xaa1faf64,0xaf64aa1f,0x2f642a1f,0xaf64aa1f,0x2f642a1f,
0xaa1f2da8,0x2f642da8,0x2a1fada8,0xaf64ada8,0x2f640000,0xaa1fb000,0xaf640000,0x2a1f3000,0xaf64ada8,0xaa1f2da8,0x2f642da8,0x2a1fada8,0x2a1f3000,0x2f648000,0xaa1fb000,0xaf640000,
0xaea7263e,0x2c722fd9,0x2ea7a63e,0xac72afd9,0x2fd92c72,0x263eaea7,0xafd9ac72,0xa63e2ea7,0xac72afd9,0xaea7263e,0x2c722fd9,0x2ea7a63e,0xa63e2ea7,0x2fd92c72,0x263eaea7,0xafd9ac72,
0xada82da8,0xada82da8,0xada82da8,0xada82da8,0x2da8ada8,0x2da8ada8,0x2da8ada8,0x2da8ada8,0x2da82da8,0x2da82da8,0x2da82da8,0x2da82da8,0xada8ada8,0xada8ada8,0xada8ada8,0xada8ada8,
0x3000,0x3000,0x3000,0x80003000,0x8000b000,0x8000b000,0x8000b000,0x8000b000,0x30000000,0x30008000,0x30008000,0x30008000,0xb0000000,0xb0000000,0xb0000000,0xb0000000,
0x2ea7263e,0xac722fd9,0xaea7a63e,0x2c72afd9,0xafd92c72,0xa63eaea7,0x2fd9ac72,0x263e2ea7,0x2c72afd9,0x2ea7263e,0xac722fd9,0xaea7a63e,0x263e2ea7,0xafd92c72,0xa63eaea7,0x2fd9ac72,
0x2f64ada8,0x2a1f2da8,0xaf642da8,0xaa1fada8,0xaa1f3000,0xaf640000,0x2a1fb000,0x2f648000,0xaa1fada8,0x2f64ada8,0x2a1f2da8,0xaf642da8,0x2f640000,0xaa1f3000,0xaf640000,0x2a1fb000,
0xaa1f2f64,0x2a1faf64,0xaa1f2f64,0x2a1faf64,0x2f64aa1f,0xaf642a1f,0x2f64aa1f,0xaf642a1f,0xaf642a1f,0x2f64aa1f,0xaf642a1f,0x2f64aa1f,0xaa1f2f64,0x2a1faf64,0xaa1f2f64,0x2a1faf64,
0x2da80000,0xada80000,0x2da88000,0xada80000,0x2da8b000,0xada83000,0x2da8b000,0xada83000,0xada83000,0x2da8b000,0xada83000,0x2da8b000,0x2da88000,0xada80000,0x2da88000,0xada88000,
0xa63e2c72,0x2fd9aea7,0x263eac72,0xafd92ea7,0xaea72fd9,0x2c72a63e,0x2ea7afd9,0xac72263e,0xafd92ea7,0xa63e2c72,0x2fd9aea7,0x263eac72,0xac72263e,0xaea72fd9,0x2c72a63e,0x2ea7afd9,
0x2f64ada8,0x2a1fada8,0xaf642da8,0xaa1f2da8,0x2a1f0000,0x2f64b000,0xaa1f0000,0xaf643000,0xaa1f2da8,0x2f64ada8,0x2a1fada8,0xaf642da8,0xaf643000,0x2a1f8000,0x2f64b000,0xaa1f8000,
0xb0003000,0xb0003000,0xb0003000,0xb0003000,0xb0003000,0xb0003000,0xb0003000,0xb0003000,0x0,0x8000,0x8000,0x80008000,0x8000,0x8000,0x8000,0x8000,
0x80000000,0x80000000,0x80008000,0x80008000,0x80000000,0x80008000,0x80008000,0x80008000,0xb0003000,0xb0003000,0xb0003000,0xb0003000,0xb0003000,0xb0003000,0xb0003000,0xb0003000,
0xaa1f2da8,0x2f64ada8,0x2a1fada8,0xaf642da8,0xaf643000,0x2a1f0000,0x2f64b000,0xaa1f8000,0xaf642da8,0xaa1f2da8,0x2f64ada8,0x2a1fada8,0xaa1f0000,0xaf643000,0x2a1f0000,0x2f64b000,
0x2fd9aea7,0x263eac72,0xafd92ea7,0xa63e2c72,0x2c72a63e,0x2ea7afd9,0xac72263e,0xaea72fd9,0xa63e2c72,0x2fd9aea7,0x263eac72,0xafd92ea7,0xaea72fd9,0x2c72a63e,0x2ea7afd9,0xac72263e,
0xada80000,0x2da80000,0xada88000,0x2da80000,0xada83000,0x2da8b000,0xada83000,0x2da8b000,0xada83000,0x2da8b000,0xada83000,0x2da8b000,0x2da80000,0xada88000,0x2da88000,0xada88000,
0xaa1f2f64,0x2a1faf64,0xaa1f2f64,0x2a1faf64,0x2f64aa1f,0xaf642a1f,0x2f64aa1f,0xaf642a1f,0x2f64aa1f,0xaf642a1f,0x2f64aa1f,0xaf642a1f,0x2a1faf64,0xaa1f2f64,0x2a1faf64,0xaa1f2f64,
0x2a1f2da8,0xaf642da8,0xaa1fada8,0x2f64ada8,0xaf640000,0x2a1fb000,0x2f640000,0xaa1f3000,0x2f64ada8,0x2a1f2da8,0xaf642da8,0xaa1fada8,0xaa1f3000,0xaf648000,0x2a1fb000,0x2f640000,
0x2c72afd9,0x2ea7263e,0xac722fd9,0xaea7a63e,0x263e2ea7,0xafd92c72,0xa63eaea7,0x2fd9ac72,0xaea7a63e,0x2c72afd9,0x2ea7263e,0xac722fd9,0x2fd9ac72,0x263e2ea7,0xafd92c72,0xa63eaea7,
0x2da8ada8,0x2da8ada8,0x2da8ada8,0x2da8ada8,0xada82da8,0xada82da8,0xada82da8,0xada82da8,0x2da82da8,0x2da82da8,0x2da82da8,0x2da82da8,0xada8ada8,0xada8ada8,0xada8ada8,0xada8ada8,
0x80003000,0x80003000,0x80003000,0x3000,0xb000,0x8000b000,0xb000,0xb000,0xb0000000,0xb0008000,0xb0008000,0xb0008000,0x30000000,0x30000000,0x30000000,0x30008000,
0x2c722fd9,0x2ea7a63e,0xac72afd9,0xaea7263e,0x263eaea7,0xafd9ac72,0xa63e2ea7,0x2fd92c72,0xaea7263e,0x2c722fd9,0x2ea7a63e,0xac72afd9,0x2fd92c72,0x263eaea7,0xafd9ac72,0xa63e2ea7,
0xaf64ada8,0xaa1f2da8,0x2f642da8,0x2a1fada8,0x2a1f3000,0x2f648000,0xaa1fb000,0xaf648000,0x2a1fada8,0xaf64ada8,0xaa1f2da8,0x2f642da8,0xaf640000,0x2a1f3000,0x2f648000,0xaa1fb000,
0x2f642a1f,0xaf64aa1f,0x2f642a1f,0xaf64aa1f,0x2a1f2f64,0xaa1faf64,0x2a1f2f64,0xaa1faf64,0xaa1faf64,0x2a1f2f64,0xaa1faf64,0x2a1f2f64,0x2f642a1f,0xaf64aa1f,0x2f642a1f,0xaf64aa1f,
0xada80000,0x2da80000,0xada88000,0x2da88000,0xada8b000,0x2da83000,0xada8b000,0x2da83000,0x2da83000,0xada8b000,0x2da83000,0xada8b000,0xada88000,0x2da88000,0xada88000,0x2da80000,
0x2fd92ea7,0x263e2c72,0xafd9aea7,0xa63eac72,0x2c72263e,0x2ea72fd9,0xac72a63e,0xaea7afd9,0xa63eac72,0x2fd92ea7,0x263e2c72,0xafd9aea7,0xaea7afd9,0x2c72263e,0x2ea72fd9,0xac72a63e,
0xaf64ada8,0xaa1fada8,0x2f642da8,0x2a1f2da8,0xaa1f0000,0xaf64b000,0x2a1f0000,0x2f643000,0x2a1f2da8,0xaf64ada8,0xaa1fada8,0x2f642da8,0x2f643000,0xaa1f8000,0xaf64b000,0x2a1f0000,
0x80008000,0x80008000,0x80008000,0x80008000,0x80008000,0x80008000,0x80008000,0x80008000,0x30003000,0x30003000,0x30003000,0x30003000,0x30003000,0x30003000,0x30003000,0x30003000,
0x80008000,0x80008000,0x80008000,0x80008000,0x80008000,0x80008000,0x80008000,0x80008000,0x30003000,0x30003000,0x30003000,0x30003000,0x30003000,0x30003000,0x30003000,0x30003000,
0xaf64ada8,0xaa1fada8,0x2f642da8,0x2a1f2da8,0xaa1f8000,0xaf64b000,0x2a1f8000,0x2f643000,0x2a1f2da8,0xaf64ada8,0xaa1fada8,0x2f642da8,0x2f643000,0xaa1f0000,0xaf64b000,0x2a1f8000,
0xafd9aea7,0xa63eac72,0x2fd92ea7,0x263e2c72,0xac72a63e,0xaea7afd9,0x2c72263e,0x2ea72fd9,0x263e2c72,0xafd9aea7,0xa63eac72,0x2fd92ea7,0x2ea72fd9,0xac72a63e,0xaea7afd9,0x2c72263e,
0x2da83000,0xada8b000,0x2da83000,0xada8b000,0xada80000,0x2da88000,0xada80000,0x2da88000,0xada88000,0x2da88000,0xada80000,0x2da88000,0xada8b000,0x2da83000,0xada8b000,0x2da83000,
0x2a1f2f64,0xaa1faf64,0x2a1f2f64,0xaa1faf64,0xaf64aa1f,0x2f642a1f,0xaf64aa1f,0x2f642a1f,0xaf64aa1f,0x2f642a1f,0xaf64aa1f,0x2f642a1f,0xaa1faf64,0x2a1f2f64,0xaa1faf64,0x2a1f2f64,
0xaf64ada8,0xaa1f2da8,0x2f642da8,0x2a1fada8,0x2a1f3000,0x2f648000,0xaa1fb000,0xaf640000,0x2a1fada8,0xaf64ada8,0xaa1f2da8,0x2f642da8,0xaf648000,0x2a1f3000,0x2f648000,0xaa1fb000,
0xac72afd9,0xaea7263e,0x2c722fd9,0x2ea7a63e,0xa63e2ea7,0x2fd92c72,0x263eaea7,0xafd9ac72,0x2ea7a63e,0xac72afd9,0xaea7263e,0x2c722fd9,0xafd9ac72,0xa63e2ea7,0x2fd92c72,0x263eaea7,
0xada8ada8,0xada8ada8,0xada8ada8,0xada8ada8,0x2da82da8,0x2da82da8,0x2da82da8,0x2da82da8,0xada82da8,0xada82da8,0xada82da8,0xada82da8,0x2da8ada8,0x2da8ada8,0x2da8ada8,0x2da8ada8,
0xb0008000,0xb0000000,0xb0000000,0xb0000000,0x30008000,0x30008000,0x30008000,0x30008000,0x3000,0x3000,0x3000,0x80003000,0x8000b000,0x8000b000,0x8000b000,0x8000b000,
0xac722fd9,0xaea7a63e,0x2c72afd9,0x2ea7263e,0xa63eaea7,0x2fd9ac72,0x263e2ea7,0xafd92c72,0x2ea7263e,0xac722fd9,0xaea7a63e,0x2c72afd9,0xafd92c72,0xa63eaea7,0x2fd9ac72,0x263e2ea7,
0x2a1f2da8,0xaf642da8,0xaa1fada8,0x2f64ada8,0xaf648000,0x2a1fb000,0x2f648000,0xaa1f3000,0x2f64ada8,0x2a1f2da8,0xaf642da8,0xaa1fada8,0xaa1f3000,0xaf640000,0x2a1fb000,0x2f648000,
0xaf642a1f,0x2f64aa1f,0xaf642a1f,0x2f64aa1f,0xaa1f2f64,0x2a1faf64,0xaa1f2f64,0x2a1faf64,0x2a1faf64,0xaa1f2f64,0x2a1faf64,0xaa1f2f64,0xaf642a1f,0x2f64aa1f,0xaf642a1f,0x2f64aa1f,
0xada83000,0x2da8b000,0xada83000,0x2da8b000,0x2da88000,0xada80000,0x2da88000,0xada88000,0xada88000,0x2da88000,0xada80000,0x2da88000,0xada83000,0x2da8b000,0xada83000,0x2da8b000,
0xafd92ea7,0xa63e2c72,0x2fd9aea7,0x263eac72,0xac72263e,0xaea72fd9,0x2c72a63e,0x2ea7afd9,0x263eac72,0xafd92ea7,0xa63e2c72,0x2fd9aea7,0x2ea7afd9,0xac72263e,0xaea72fd9,0x2c72a63e,
0xaa1f2da8,0x2f64ada8,0x2a1fada8,0xaf642da8,0xaf643000,0x2a1f8000,0x2f64b000,0xaa1f8000,0xaf642da8,0xaa1f2da8,0x2f64ada8,0x2a1fada8,0xaa1f8000,0xaf643000,0x2a1f8000,0x2f64b000,
0x80008000,0x80000000,0x80000000,0x0,0x80000000,0x80000000,0x80000000,0x80000000,0xb0003000,0xb0003000,0xb0003000,0xb0003000,0xb0003000,0xb0003000,0xb0003000,0xb0003000,
0x3000b000,0x3000b000,0x3000b000,0x3000b000,0x3000b000,0x3000b000,0x3000b000,0x3000b000,0x80000000,0x80000000,0x80008000,0x80008000,0x80000000,0x80008000,0x80008000,0x80008000,
0x2f64ada8,0x2a1fada8,0xaf642da8,0xaa1f2da8,0x2a1f8000,0x2f64b000,0xaa1f8000,0xaf643000,0xaa1f2da8,0x2f64ada8,0x2a1fada8,0xaf642da8,0xaf643000,0x2a1f0000,0x2f64b000,0xaa1f8000,
0x263eac72,0xafd92ea7,0xa63e2c72,0x2fd9aea7,0x2ea7afd9,0xac72263e,0xaea72fd9,0x2c72a63e,0x2fd9aea7,0x263eac72,0xafd92ea7,0xa63e2c72,0x2c72a63e,0x2ea7afd9,0xac72263e,0xaea72fd9,
0xada83000,0x2da8b000,0xada83000,0x2da8b000,0x2da80000,0xada88000,0x2da88000,0xada88000,0x2da88000,0xada88000,0x2da80000,0xada88000,0x2da8b000,0xada83000,0x2da8b000,0xada83000,
0x2f64aa1f,0xaf642a1f,0x2f64aa1f,0xaf642a1f,0x2a1faf64,0xaa1f2f64,0x2a1faf64,0xaa1f2f64,0x2a1faf64,0xaa1f2f64,0x2a1faf64,0xaa1f2f64,0xaf642a1f,0x2f64aa1f,0xaf642a1f,0x2f64aa1f,
0x2f64ada8,0x2a1f2da8,0xaf642da8,0xaa1fada8,0xaa1f3000,0xaf648000,0x2a1fb000,0x2f640000,0xaa1fada8,0x2f64ada8,0x2a1f2da8,0xaf642da8,0x2f648000,0xaa1f3000,0xaf648000,0x2a1fb000,
0xaea7a63e,0x2c72afd9,0x2ea7263e,0xac722fd9,0x2fd9ac72,0x263e2ea7,0xafd92c72,0xa63eaea7,0xac722fd9,0xaea7a63e,0x2c72afd9,0x2ea7263e,0xa63eaea7,0x2fd9ac72,0x263e2ea7,0xafd92c72,
0xada8ada8,0xada8ada8,0xada8ada8,0xada8ada8,0x2da82da8,0x2da82da8,0x2da82da8,0x2da82da8,0x2da8ada8,0x2da8ada8,0x2da8ada8,0x2da8ada8,0xada82da8,0xada82da8,0xada82da8,0xada82da8,
0x30008000,0x30000000,0x30000000,0x30000000,0xb0008000,0xb0008000,0xb0008000,0xb0000000,0x80003000,0x80003000,0x80003000,0x3000,0xb000,0x8000b000,0xb000,0xb000,
0x2ea7a63e,0xac72afd9,0xaea7263e,0x2c722fd9,0xafd9ac72,0xa63e2ea7,0x2fd92c72,0x263eaea7,0x2c722fd9,0x2ea7a63e,0xac72afd9,0xaea7263e,0x263eaea7,0xafd9ac72,0xa63e2ea7,0x2fd92c72,
0xaa1f2da8,0x2f642da8,0x2a1fada8,0xaf64ada8,0x2f648000,0xaa1fb000,0xaf640000,0x2a1f3000,0xaf64ada8,0xaa1f2da8,0x2f642da8,0x2a1fada8,0x2a1f3000,0x2f648000,0xaa1fb000,0xaf648000,
0xaa1faf64,0x2a1f2f64,0xaa1faf64,0x2a1f2f64,0x2f642a1f,0xaf64aa1f,0x2f642a1f,0xaf64aa1f,0xaf64aa1f,0x2f642a1f,0xaf64aa1f,0x2f642a1f,0xaa1faf64,0x2a1f2f64,0xaa1faf64,0x2a1f2f64,
0x2da83000,0xada8b000,0x2da83000,0xada8b000,0xada88000,0x2da88000,0xada88000,0x2da80000,0x2da88000,0xada88000,0x2da80000,0xada80000,0x2da83000,0xada8b000,0x2da83000,0xada8b000,
0xa63eac72,0x2fd92ea7,0x263e2c72,0xafd9aea7,0xaea7afd9,0x2c72263e,0x2ea72fd9,0xac72a63e,0xafd9aea7,0xa63eac72,0x2fd92ea7,0x263e2c72,0xac72a63e,0xaea7afd9,0x2c72263e,0x2ea72fd9,
0x2a1f2da8,0xaf64ada8,0xaa1fada8,0x2f642da8,0x2f643000,0xaa1f8000,0xaf64b000,0x2a1f0000,0x2f642da8,0x2a1f2da8,0xaf64ada8,0xaa1fada8,0x2a1f8000,0x2f643000,0xaa1f8000,0xaf64b000,
0x3c003c00,0x3c003c00,0x3c003c00,0x3c003c00,0x3c003c00,0x3c003c00,0x3c003c00,0x3c003c00,0x80008000,0x80008000,0x80008000,0x80008000,0x80008000,0x80008000,0x80008000,0x80008000,
0x3bd93c00,0x3aa73b64,0x387239a8,0x323e361f,0xb23e0000,0xb872b61f,0xbaa7b9a8,0xbbd9bb64,0xb23e8000,0xb872b61f,0xbaa7b9a8,0xbbd9bb64,0xbbd9bc00,0xbaa7bb64,0xb872b9a8,0xb23eb61f,
0xbb64bc00,0xb61fb9a8,0x361f8000,0x3b6439a8,0x3b643c00,0x361f39a8,0xb61f0000,0xbb64b9a8,0x361f8000,0x3b6439a8,0x3b643c00,0x361f39a8,0xb61f8000,0xbb64b9a8,0xbb64bc00,0xb61fb9a8,
0x38728000,0x3bd93b64,0x323e39a8,0xbaa7b61f,0x3aa73c00,0xb23e361f,0xbbd9b9a8,0xb872bb64,0x3aa73c00,0xb23e361f,0xbbd9b9a8,0xb872bb64,0xb8728000,0xbbd9bb64,0xb23eb9a8,0x3aa7361f,
0xbc008000,0x3c008000,0xbc000000,0x3c008000,0xbc000000,0x3c008000,0xbc000000,0x3c008000,0x3c00,0x8000bc00,0x3c00,0x8000bc00,0x3c00,0x8000bc00,0x80003c00,0x8000bc00,
0xbbd98000,0x3aa7361f,0xb872b9a8,0x323e3b64,0x323ebc00,0xb8723b64,0x3aa7b9a8,0xbbd9361f,0xb23e3c00,0x3872bb64,0xbaa739a8,0x3bd9b61f,0xbbd90000,0x3aa7361f,0xb872b9a8,0x323e3b64,
0x3b648000,0xb61fb9a8,0xb61f3c00,0x3b64b9a8,0xbb648000,0x361f39a8,0x361fbc00,0xbb6439a8,0x361fbc00,0xbb6439a8,0x3b648000,0xb61fb9a8,0xb61f3c00,0x3b64b9a8,0xbb640000,0x361f39a8,
0xb8723c00,0x3bd9b61f,0xb23eb9a8,0xbaa73b64,0xbaa78000,0xb23e3b64,0x3bd9b9a8,0xb872b61f,0x3aa78000,0x323ebb64,0xbbd939a8,0x3872361f,0xb8723c00,0x3bd9b61f,0xb23eb9a8,0xbaa73b64,
0xbbd93c00,0xbaa73b64,0xb87239a8,0xb23e361f,0x323e8000,0x3872b61f,0x3aa7b9a8,0x3bd9bb64,0x323e8000,0x3872b61f,0x3aa7b9a8,0x3bd9bb64,0x3bd9bc00,0x3aa7bb64,0x3872b9a8,0x323eb61f,
0xbc003c00,0xbc003c00,0xbc003c00,0xbc003c00,0xbc003c00,0xbc003c00,0xbc003c00,0xbc003c00,0x80008000,0x80000000,0x80000000,0x80000000,0x80000000,0x80000000,0x0,0x80000000,
0xb8728000,0xbbd93b64,0xb23e39a8,0x3aa7b61f,0xbaa73c00,0x323e361f,0x3bd9b9a8,0x3872bb64,0xbaa73c00,0x323e361f,0x3bd9b9a8,0x3872bb64,0x38728000,0x3bd9bb64,0x323eb9a8,0xbaa7361f,
0x3b64bc00,0x361fb9a8,0xb61f8000,0xbb6439a8,0xbb643c00,0xb61f39a8,0x361f0000,0x3b64b9a8,0xb61f8000,0xbb6439a8,0xbb643c00,0xb61f39a8,0x361f8000,0x3b64b9a8,0x3b64bc00,0x361fb9a8,
0x3bd98000,0xbaa7361f,0x3872b9a8,0xb23e3b64,0xb23ebc00,0x38723b64,0xbaa7b9a8,0x3bd9361f,0x323e3c00,0xb872bb64,0x3aa739a8,0xbbd9b61f,0x3bd98000,0xbaa7361f,0x3872b9a8,0xb23e3b64,
0x3c008000,0xbc008000,0x3c000000,0xbc008000,0x3c000000,0xbc008000,0x3c000000,0xbc000000,0x80003c00,0xbc00,0x80003c00,0x8000bc00,0x80003c00,0xbc00,0x80003c00,0xbc00,
0x38723c00,0xbbd9b61f,0x323eb9a8,0x3aa73b64,0x3aa78000,0x323e3b64,0xbbd9b9a8,0x3872b61f,0xbaa78000,0xb23ebb64,0x3bd939a8,0xb872361f,0x38723c00,0xbbd9b61f,0x323eb9a8,0x3aa73b64,
0xbb640000,0x361fb9a8,0x361f3c00,0xbb64b9a8,0x3b648000,0xb61f39a8,0xb61fbc00,0x3b6439a8,0xb61fbc00,0x3b6439a8,0xbb640000,0x361fb9a8,0x361f3c00,0xbb64b9a8,0x3b648000,0xb61f39a8,
0x39a83c00,0xb9a80000,0xb9a8bc00,0x39a88000,0x39a83c00,0xb9a80000,0xb9a8bc00,0x39a88000,0xb9a88000,0xb9a8bc00,0x39a88000,0x39a83c00,0xb9a80000,0xb9a8bc00,0x39a88000,0x39a83c00,
0x38723c00,0xbbd9b61f,0x323eb9a8,0x3aa73b64,0xbaa70000,0xb23ebb64,0x3bd939a8,0xb872361f,0xbaa78000,0xb23ebb64,0x3bd939a8,0xb872361f,0xb872bc00,0x3bd9361f,0xb23e39a8,0xbaa7bb64,
0xb61fbc00,0x3b6439a8,0xbb640000,0x361fb9a8,0x361f3c00,0xbb64b9a8,0x3b648000,0xb61f39a8,0x3b648000,0xb61f39a8,0xb61fbc00,0x3b6439a8,0xbb648000,0x361fb9a8,0x361f3c00,0xbb64b9a8,
0x3bd98000,0xbaa7361f,0x3872b9a8,0xb23e3b64,0x323e3c00,0xb872bb64,0x3aa739a8,0xbbd9b61f,0x323e3c00,0xb872bb64,0x3aa739a8,0xbbd9b61f,0xbbd98000,0x3aa7b61f,0xb87239a8,0x323ebb64,
0xb9a88000,0xb9a83c00,0x39a88000,0x39a8bc00,0xb9a80000,0xb9a83c00,0x39a88000,0x39a8bc00,0xb9a83c00,0x39a88000,0x39a8bc00,0xb9a80000,0xb9a83c00,0x39a88000,0x39a8bc00,0xb9a88000,
0xb8728000,0xbbd93b64,0xb23e39a8,0x3aa7b61f,0x3aa7bc00,0xb23eb61f,0xbbd939a8,0xb8723b64,0xbaa73c00,0x323e361f,0x3bd9b9a8,0x3872bb64,0xb8728000,0xbbd93b64,0xb23e39a8,0x3aa7b61f,
0x361f8000,0x3b64b9a8,0x3b64bc00,0x361fb9a8,0xb61f8000,0xbb6439a8,0xbb643c00,0xb61f39a8,0x3b64bc00,0x361fb9a8,0xb61f8000,0xbb6439a8,0xbb643c00,0xb61f39a8,0x361f8000,0x3b64b9a8,
0xbbd93c00,0xbaa73b64,0xb87239a8,0xb23e361f,0xb23e8000,0xb872361f,0xbaa739a8,0xbbd93b64,0x323e8000,0x3872b61f,0x3aa7b9a8,0x3bd9bb64,0xbbd93c00,0xbaa73b64,0xb87239a8,0xb23e361f,
0xb8723c00,0x3bd9b61f,0xb23eb9a8,0xbaa73b64,0x3aa78000,0x323ebb64,0xbbd939a8,0x3872361f,0x3aa78000,0x323ebb64,0xbbd939a8,0x3872361f,0x3872bc00,0xbbd9361f,0x323e39a8,0x3aa7bb64,
0xb9a83c00,0x39a80000,0x39a8bc00,0xb9a88000,0xb9a83c00,0x39a88000,0x39a8bc00,0xb9a88000,0x39a88000,0x39a8bc00,0xb9a88000,0xb9a83c00,0x39a80000,0x39a8bc00,0xb9a88000,0xb9a83c00,
0xbbd98000,0x3aa7361f,0xb872b9a8,0x323e3b64,0xb23e3c00,0x3872bb64,0xbaa739a8,0x3bd9b61f,0xb23e3c00,0x3872bb64,0xbaa739a8,0x3bd9b61f,0x3bd98000,0xbaa7b61f,0x387239a8,0xb23ebb64,
0x361fbc00,0xbb6439a8,0x3b640000,0xb61fb9a8,0xb61f3c00,0x3b64b9a8,0xbb648000,0x361f39a8,0xbb648000,0x361f39a8,0x361fbc00,0xbb6439a8,0x3b648000,0xb61fb9a8,0xb61f3c00,0x3b64b9a8,
0x38728000,0x3bd93b64,0x323e39a8,0xbaa7b61f,0xbaa7bc00,0x323eb61f,0x3bd939a8,0x38723b64,0x3aa73c00,0xb23e361f,0xbbd9b9a8,0xb872bb64,0x38728000,0x3bd93b64,0x323e39a8,0xbaa7b61f,
0x39a88000,0x39a83c00,0xb9a88000,0xb9a8bc00,0x39a80000,0x39a83c00,0xb9a80000,0xb9a8bc00,0x39a83c00,0xb9a88000,0xb9a8bc00,0x39a88000,0x39a83c00,0xb9a88000,0xb9a8bc00,0x39a80000,
0x3bd93c00,0x3aa73b64,0x387239a8,0x323e361f,0x323e8000,0x3872361f,0x3aa739a8,0x3bd93b64,0xb23e8000,0xb872b61f,0xbaa7b9a8,0xbbd9bb64,0x3bd93c00,0x3aa73b64,0x387239a8,0x323e361f,
0xb61f8000,0xbb64b9a8,0xbb64bc00,0xb61fb9a8,0x361f8000,0x3b6439a8,0x3b643c00,0x361f39a8,0xbb64bc00,0xb61fb9a8,0x361f0000,0x3b6439a8,0x3b643c00,0x361f39a8,0xb61f8000,0xbb64b9a8,
0x0,0x0,0x0,0x0,0x0,0x0,0x0,0x0,0x3c003c00,0x3c003c00,0x3c003c00,0x3c003c00,0x3c003c00,0x3c003c00,0x3c003c00,0x3c003c00,
0x323e0000,0x3872361f,0x3aa739a8,0x3bd93b64,0x3bd93c00,0x3aa73b64,0x387239a8,0x323e361f,0x3bd93c00,0x3aa73b64,0x387239a8,0x323e361f,0xb23e0000,0xb872b61f,0xbaa7b9a8,0xbbd9bb64,
0xb61f0000,0xbb64b9a8,0xbb64bc00,0xb61fb9a8,0x361f0000,0x3b6439a8,0x3b643c00,0x361f39a8,0xbb64bc00,0xb61fb9a8,0x361f8000,0x3b6439a8,0x3b643c00,0x361f39a8,0xb61f0000,0xbb64b9a8,
0xbaa7bc00,0x323eb61f,0x3bd939a8,0x38723b64,0x38720000,0x3bd93b64,0x323e39a8,0xbaa7b61f,0x38728000,0x3bd93b64,0x323e39a8,0xbaa7b61f,0x3aa73c00,0xb23e361f,0xbbd9b9a8,0xb872bb64,
0x3c00,0x8000bc00,0x3c00,0x8000bc00,0x3c00,0x8000bc00,0x80003c00,0x8000bc00,0x3c000000,0xbc000000,0x3c008000,0xbc000000,0x3c008000,0xbc000000,0x3c008000,0xbc000000,
0xb23e3c00,0x3872bb64,0xbaa739a8,0x3bd9b61f,0xbbd90000,0x3aa7361f,0xb872b9a8,0x323e3b64,0x3bd90000,0xbaa7b61f,0x387239a8,0xb23ebb64,0xb23e3c00,0x3872bb64,0xbaa739a8,0x3bd9b61f,
0x361fbc00,0xbb6439a8,0x3b648000,0xb61fb9a8,0xb61f3c00,0x3b64b9a8,0xbb640000,0x361f39a8,0xbb640000,0x361f39a8,0x361fbc00,0xbb6439a8,0x3b640000,0xb61fb9a8,0xb61f3c00,0x3b64b9a8,
0x3aa78000,0x323ebb64,0xbbd939a8,0x3872361f,0xb8723c00,0x3bd9b61f,0xb23eb9a8,0xbaa73b64,0x3872bc00,0xbbd9361f,0x323e39a8,0x3aa7bb64,0x3aa70000,0x323ebb64,0xbbd939a8,0x3872361f,
0xb23e0000,0xb872361f,0xbaa739a8,0xbbd93b64,0xbbd93c00,0xbaa73b64,0xb87239a8,0xb23e361f,0xbbd93c00,0xbaa73b64,0xb87239a8,0xb23e361f,0x323e8000,0x3872b61f,0x3aa7b9a8,0x3bd9bb64,
0x0,0x8000,0x8000,0x8000,0x8000,0x8000,0x80008000,0x8000,0xbc003c00,0xbc003c00,0xbc003c00,0xbc003c00,0xbc003c00,0xbc003c00,0xbc003c00,0xbc003c00,
0x3aa7bc00,0xb23eb61f,0xbbd939a8,0xb8723b64,0xb8720000,0xbbd93b64,0xb23e39a8,0x3aa7b61f,0xb8728000,0xbbd93b64,0xb23e39a8,0x3aa7b61f,0xbaa73c00,0x323e361f,0x3bd9b9a8,0x3872bb64,
0x361f0000,0x3b64b9a8,0x3b64bc00,0x361fb9a8,0xb61f0000,0xbb6439a8,0xbb643c00,0xb61f39a8,0x3b64bc00,0x361fb9a8,0xb61f8000,0xbb6439a8,0xbb643c00,0xb61f39a8,0x361f0000,0x3b64b9a8,
0x323e3c00,0xb872bb64,0x3aa739a8,0xbbd9b61f,0x3bd98000,0xbaa7361f,0x3872b9a8,0xb23e3b64,0xbbd90000,0x3aa7b61f,0xb87239a8,0x323ebb64,0x323e3c00,0xb872bb64,0x3aa739a8,0xbbd9b61f,
0x80003c00,0xbc00,0x80003c00,0x8000bc00,0x80003c00,0xbc00,0x80003c00,0xbc00,0xbc000000,0x3c000000,0xbc008000,0x3c000000,0xbc008000,0x3c000000,0xbc008000,0x3c008000,
0xbaa78000,0xb23ebb64,0x3bd939a8,0xb872361f,0x38723c00,0xbbd9b61f,0x323eb9a8,0x3aa73b64,0xb872bc00,0x3bd9361f,0xb23e39a8,0xbaa7bb64,0xbaa70000,0xb23ebb64,0x3bd939a8,0xb872361f,
0xb61fbc00,0x3b6439a8,0xbb640000,0x361fb9a8,0x361f3c00,0xbb64b9a8,0x3b648000,0xb61f39a8,0x3b648000,0xb61f39a8,0xb61fbc00,0x3b6439a8,0xbb640000,0x361fb9a8,0x361f3c00,0xbb64b9a8,
0x39a80000,0x39a83c00,0xb9a80000,0xb9a8bc00,0x39a88000,0x39a83c00,0xb9a80000,0xb9a8bc00,0x39a83c00,0xb9a80000,0xb9a8bc00,0x39a88000,0x39a83c00,0xb9a80000,0xb9a8bc00,0x39a88000,
0x3aa70000,0x323e3b64,0xbbd9b9a8,0x3872b61f,0x38723c00,0xbbd9b61f,0x323eb9a8,0x3aa73b64,0x38723c00,0xbbd9b61f,0x323eb9a8,0x3aa73b64,0xbaa70000,0xb23ebb64,0x3bd939a8,0xb872361f,
0xbb640000,0x361fb9a8,0x361f3c00,0xbb64b9a8,0x3b640000,0xb61f39a8,0xb61fbc00,0x3b6439a8,0xb61fbc00,0x3b6439a8,0xbb640000,0x361fb9a8,0x361f3c00,0xbb64b9a8,0x3b648000,0xb61f39a8,
0xb23ebc00,0x38723b64,0xbaa7b9a8,0x3bd9361f,0x3bd90000,0xbaa7361f,0x3872b9a8,0xb23e3b64,0x3bd98000,0xbaa7361f,0x3872b9a8,0xb23e3b64,0x323e3c00,0xb872bb64,0x3aa739a8,0xbbd9b61f,
0xb9a83c00,0x39a88000,0x39a8bc00,0xb9a80000,0xb9a83c00,0x39a88000,0x39a8bc00,0xb9a88000,0x39a80000,0x39a8bc00,0xb9a80000,0xb9a83c00,0x39a88000,0x39a8bc00,0xb9a80000,0xb9a83c00,
0xbaa73c00,0x323e361f,0x3bd9b9a8,0x3872bb64,0xb8728000,0xbbd93b64,0xb23e39a8,0x3aa7b61f,0x38720000,0x3bd9bb64,0x323eb9a8,0xbaa7361f,0xbaa73c00,0x323e361f,0x3bd9b9a8,0x3872bb64,
0x3b64bc00,0x361fb9a8,0xb61f8000,0xbb6439a8,0xbb643c00,0xb61f39a8,0x361f8000,0x3b64b9a8,0xb61f0000,0xbb6439a8,0xbb643c00,0xb61f39a8,0x361f0000,0x3b64b9a8,0x3b64bc00,0x361fb9a8,
0x323e8000,0x3872b61f,0x3aa7b9a8,0x3bd9bb64,0xbbd93c00,0xbaa73b64,0xb87239a8,0xb23e361f,0x3bd9bc00,0x3aa7bb64,0x3872b9a8,0x323eb61f,0x323e0000,0x3872b61f,0x3aa7b9a8,0x3bd9bb64,
0xbaa70000,0xb23e3b64,0x3bd9b9a8,0xb872b61f,0xb8723c00,0x3bd9b61f,0xb23eb9a8,0xbaa73b64,0xb8723c00,0x3bd9b61f,0xb23eb9a8,0xbaa73b64,0x3aa78000,0x323ebb64,0xbbd939a8,0x3872361f,
0xb9a80000,0xb9a83c00,0x39a80000,0x39a8bc00,0xb9a88000,0xb9a83c00,0x39a80000,0x39a8bc00,0xb9a83c00,0x39a80000,0x39a8bc00,0xb9a88000,0xb9a83c00,0x39a88000,0x39a8bc00,0xb9a88000,
0x323ebc00,0xb8723b64,0x3aa7b9a8,0xbbd9361f,0xbbd90000,0x3aa7361f,0xb872b9a8,0x323e3b64,0xbbd98000,0x3aa7361f,0xb872b9a8,0x323e3b64,0xb23e3c00,0x3872bb64,0xbaa739a8,0x3bd9b61f,
0x3b640000,0xb61fb9a8,0xb61f3c00,0x3b64b9a8,0xbb640000,0x361f39a8,0x361fbc00,0xbb6439a8,0x361fbc00,0xbb6439a8,0x3b640000,0xb61fb9a8,0xb61f3c00,0x3b64b9a8,0xbb648000,0x361f39a8,
0x3aa73c00,0xb23e361f,0xbbd9b9a8,0xb872bb64,0x38728000,0x3bd93b64,0x323e39a8,0xbaa7b61f,0xb8720000,0xbbd9bb64,0xb23eb9a8,0x3aa7361f,0x3aa73c00,0xb23e361f,0xbbd9b9a8,0xb872bb64,
0x39a83c00,0xb9a88000,0xb9a8bc00,0x39a88000,0x39a83c00,0xb9a88000,0xb9a8bc00,0x39a80000,0xb9a80000,0xb9a8bc00,0x39a80000,0x39a83c00,0xb9a88000,0xb9a8bc00,0x39a88000,0x39a83c00,
0xb23e8000,0xb872b61f,0xbaa7b9a8,0xbbd9bb64,0x3bd93c00,0x3aa73b64,0x387239a8,0x323e361f,0xbbd9bc00,0xbaa7bb64,0xb872b9a8,0xb23eb61f,0xb23e0000,0xb872b61f,0xbaa7b9a8,0xbbd9bb64,
0xbb64bc00,0xb61fb9a8,0x361f0000,0x3b6439a8,0x3b643c00,0x361f39a8,0xb61f8000,0xbb64b9a8,0x361f0000,0x3b6439a8,0x3b643c00,0x361f39a8,0xb61f0000,0xbb64b9a8,0xbb64bc00,0xb61fb9a8,
};
__device__ __align__(1024) bf16 g_x1T[DM * XP];
__device__ __align__(1024) bf16 g_x2T[2][DM * XP];
__device__ __align__(1024) float g_sums[2][2][SEQ];

#define TS_SMEM 0
#define TS_DECL
#define TS_ARG
#define TS_PASS
#define TS_PHASE(p)
#define TS(i)
#define TSX(row, i)
#define TS_BEGIN
#define TS_END

struct cplx { float r, i; };
__device__ __forceinline__ cplx cmul(cplx a, cplx b) {
    cplx o;
    o.r = fmaf(a.r, b.r, -a.i * b.i);
    o.i = fmaf(a.r, b.i, a.i * b.r);
    return o;
}
__device__ __forceinline__ cplx csq(cplx a) {
    cplx o;
    o.r = fmaf(a.r, a.r, -a.i * a.i);
    o.i = 2.f * a.r * a.i;
    return o;
}
__device__ __forceinline__ cplx cexp_p(float arl, float ai, float p) {
    float mag = ex2(arl * p);
    float ang = ai * p;
    float n = rintf(ang * 0.15915494309189535f);
    float r = fmaf(n, -6.2831854820251465f, ang);
    r = fmaf(n, 1.7484555e-7f, r);
    cplx o;
    o.r = mag * __cosf(r);
    o.i = mag * __sinf(r);
    return o;
}

__device__ __forceinline__ uint32_t pack2h(float lo, float hi) {
    uint32_t r;
    asm("cvt.rn.f16x2.f32 %0, %1, %2;" : "=r"(r) : "f"(hi), "f"(lo));
    return r;
}
__device__ __forceinline__ uint32_t hmul(uint32_t a, uint32_t b) { uint32_t d; asm("mul.rn.f16x2 %0, %1, %2;" : "=r"(d) : "r"(a), "r"(b)); return d; }
__device__ __forceinline__ uint32_t hfma(uint32_t a, uint32_t b, uint32_t c) { uint32_t d; asm("fma.rn.f16x2 %0, %1, %2, %3;" : "=r"(d) : "r"(a), "r"(b), "r"(c)); return d; }
__device__ __forceinline__ uint32_t hfms(uint32_t a, uint32_t b, uint32_t c) {
    uint32_t d;
    asm("{\n.reg .b32 n;\nneg.f16x2 n, %1;\nfma.rn.f16x2 %0, n, %2, %3;\n}" : "=r"(d) : "r"(a), "r"(b), "r"(c));
    return d;
}
__device__ __forceinline__ uint32_t hadd(uint32_t a, uint32_t b) { uint32_t d; asm("add.rn.f16x2 %0, %1, %2;" : "=r"(d) : "r"(a), "r"(b)); return d; }
__device__ __forceinline__ uint32_t hsub(uint32_t a, uint32_t b) { uint32_t d; asm("sub.rn.f16x2 %0, %1, %2;" : "=r"(d) : "r"(a), "r"(b)); return d; }
__device__ __forceinline__ uint4 ldg_tab(int tab, int t) {
    uint4 v;
    asm volatile("ld.global.nc.v4.u32 {%0,%1,%2,%3}, [%4];" : "=r"(v.x), "=r"(v.y), "=r"(v.z), "=r"(v.w) : "l"((const uint4*)c_fft + tab * 128 + t));
    return v;
}
__device__ __forceinline__ uint32_t u4(const uint4& v, int i) { return i == 0 ? v.x : i == 1 ? v.y : i == 2 ? v.z : v.w; }
struct cpair { uint32_t r, i; };
__device__ __forceinline__ cpair pmul(cpair p, uint32_t z) {
    const __half2 zv = *reinterpret_cast<const __half2*>(&z), pr = *reinterpret_cast<const __half2*>(&p.r), pi = *reinterpret_cast<const __half2*>(&p.i);
    const __half2 zr = __low2half2(zv), zi = __high2half2(zv);
    const __half2 a = __hfma2(__hneg2(pi), zi, __hmul2(pr, zr)), b = __hfma2(pi, zr, __hmul2(pr, zi));
    return {*reinterpret_cast<const uint32_t*>(&a), *reinterpret_cast<const uint32_t*>(&b)};
}
__device__ __forceinline__ uint32_t packz(cplx z) { return pack2h(z.r, z.i); }
__device__ __forceinline__ void wgmma_kg(float (&d)[24], uint64_t da, uint64_t db, int scale_d) {
    asm volatile("{\n.reg .pred p;\nsetp.ne.b32 p, %26, 0;\n"
                 "wgmma.mma_async.sync.aligned.m64n48k16.f32.f16.f16 "
                 "{%0,%1,%2,%3,%4,%5,%6,%7,%8,%9,%10,%11,%12,%13,%14,%15,%16,%17,%18,%19,%20,%21,%22,%23}, %24, %25, p, 1, 1, 1, 1;\n}\n"
                 : "+f"(d[0]), "+f"(d[1]), "+f"(d[2]), "+f"(d[3]), "+f"(d[4]), "+f"(d[5]), "+f"(d[6]), "+f"(d[7]), "+f"(d[8]), "+f"(d[9]),
                   "+f"(d[10]), "+f"(d[11]), "+f"(d[12]), "+f"(d[13]), "+f"(d[14]), "+f"(d[15]), "+f"(d[16]), "+f"(d[17]), "+f"(d[18]), "+f"(d[19]),
                   "+f"(d[20]), "+f"(d[21]), "+f"(d[22]), "+f"(d[23])
                 : "l"(da), "l"(db), "r"(scale_d));
}

struct SsmParams { const bf16 *lar, *aim, *cre, *cim, *logdt, *dskip; };
constexpr int KG_TABLES = 6 * 16384, KG_RES = 1664;
struct KgShared { uint32_t kmax[6], kexp[6]; float cinv[6]; };
struct KgParams { uint32_t l[3], a[3], r[3], i[3], dt, ds; };

__device__ __forceinline__ bool kg_is_hi(int warp) { return ((warp >> 1) ^ (warp >> 2)) & 1; }
__device__ __forceinline__ void kgen_load(KgParams& kp, int d0, int warp, int lane, const SsmParams& sp) {
    const int d = d0 + min(2 * (warp >> 2) + (warp & 1), 4), idx = d * (NMODE / 2) + lane;
    const bf16 *pr = kg_is_hi(warp) ? sp.cre : sp.lar, *pi = kg_is_hi(warp) ? sp.cim : sp.aim;
    kp.dt = __ldg((const uint16_t*)sp.logdt + d);
#pragma unroll
    for (int j = 0; j < 3; j++) {
        kp.l[j] = __ldg((const uint32_t*)sp.lar + idx + 32 * j); kp.a[j] = __ldg((const uint32_t*)sp.aim + idx + 32 * j);
        kp.r[j] = __ldg((const uint32_t*)pr + idx + 32 * j); kp.i[j] = __ldg((const uint32_t*)pi + idx + 32 * j);
    }
    kp.ds = __ldg((const uint16_t*)sp.dskip + d0 + min(warp >> 1, 4));
}

struct KgAnchors { uint32_t v[8]; };
__device__ __forceinline__ KgAnchors kg_anchor_lo(const KgParams& kp, uint32_t sel, float dt) {
    auto B = [&](uint32_t v) { return __uint_as_float(__byte_perm(v, 0u, sel)); };
    const float arl = -rbf(ex2(B(kp.l[0]) * 1.4426950408889634f)) * dt * 1.4426950408889634f, ai = B(kp.a[0]) * dt;
    const cplx z8 = cexp_p(arl, ai, 8.f), z16 = csq(z8), z24 = cmul(z16, z8), z32 = csq(z16), z64 = csq(z32), z128 = csq(z64), z192 = cmul(z128, z64);
    return {{pack2h(1.f, z8.r), pack2h(0.f, z8.i), pack2h(z16.r, z24.r), pack2h(z16.i, z24.i), packz(z32), packz(z64), packz(z128), packz(z192)}};
}
__device__ __forceinline__ KgAnchors kg_anchor_hi(const KgParams& kp, uint32_t sel, float dt, float cs) {
    auto B = [&](uint32_t v) { return __uint_as_float(__byte_perm(v, 0u, sel)); };
    const float arl = -rbf(ex2(B(kp.l[0]) * 1.4426950408889634f)) * dt * 1.4426950408889634f, ai = B(kp.a[0]) * dt;
    const cplx z1 = cexp_p(arl, -ai, 1.f), z2 = csq(z1), z4 = csq(z2), z256 = cexp_p(arl, -ai, 256.f), z512 = csq(z256), z1024 = csq(z512);
    const cplx H0 = {B(kp.r[0]) * cs, -B(kp.i[0]) * cs}, H4 = cmul(H0, z4);
    return {{pack2h(H0.r, H4.r), pack2h(H0.i, H4.i), packz(z1), packz(z2), packz(z256), packz(z512), packz(z1024), 0u}};
}

__device__ __forceinline__ void kgen_tables(KgParams& kp, uint32_t scr, uint32_t dump, KgShared* ks, int warp, int lane TS_ARG) {
    const int wg = warp >> 2, half = warp & 1, sw = lane & 7;
    const bool hi = kg_is_hi(warp);
    TS(23);
    const float dt = rbf(ex2(bf_lo(kp.dt) * 1.4426950408889634f));
    uint32_t sel = (wg == 2 && half) ? 0x3244u : 0x1044u;
    float cs = 0.f;
    KgAnchors an;
    if (hi) {
        uint32_t m = 0;
#pragma unroll
        for (int j = 0; j < 3; j++) m = __vmaxu2(m, __vmaxu2(kp.r[j] & 0x7FFF7FFFu, kp.i[j] & 0x7FFF7FFFu));
        m = __reduce_max_sync(~0u, max(m << 16, m & 0xFFFF0000u));
        const uint32_t e = min(max(__float_as_uint(2.f * dt * __uint_as_float(m)) >> 23, 2u), 252u);
        cs = 2.f * dt * __uint_as_float((253u - e) << 23);
        if (lane == 0) { ks->cinv[2 * wg + half] = __uint_as_float((e + 1u) << 23); ks->kmax[2 * wg + half] = 0u; }
        an = kg_anchor_hi(kp, sel, dt, cs);
    } else {
        an = kg_anchor_lo(kp, sel, dt);
    }
    float acc[24];
#pragma unroll
    for (int i = 0; i < 24; i++) acc[i] = 0.f;
    uint32_t tb = scr + 2 * wg * 16384 + lane * 128;
    uint64_t da = mkdesc(scr + 2 * wg * 16384, 4096, 1024, 1);
    int flip = 16384;
#pragma unroll 1
    for (int c = wg == 2 ? 1 : 0, step = wg == 2 ? 2 : 1; c < 6; c += step) {
        if (wg < 2) sel ^= 0x2200u;
        if (!hi) {
            if (c & 1) { kp.l[0] = kp.l[1]; kp.l[1] = kp.l[2]; kp.a[0] = kp.a[1]; kp.a[1] = kp.a[2]; }
            cpair p[4];
            p[0] = {an.v[0], an.v[1]}; p[1] = {an.v[2], an.v[3]};
            p[2] = pmul(p[0], an.v[4]); p[3] = pmul(p[1], an.v[4]);
#pragma unroll
            for (int j = 0; j < 4; j++) {
                cpair v[4];
#pragma unroll
                for (int i = 0; i < 4; i++) v[i] = j ? pmul(p[i], an.v[4 + j]) : p[i];
                const uint32_t a = tb + (((4 * half + j) ^ sw) << 4);
                sts128(a, make_uint4(v[0].r, v[1].r, v[2].r, v[3].r));
                sts128(a + 4096, make_uint4(v[0].i, v[1].i, v[2].i, v[3].i));
            }
            an = kg_anchor_lo(kp, sel, dt);
        } else {
            if (c & 1) {
#pragma unroll
                for (int j = 0; j < 2; j++) { kp.l[j] = kp.l[j + 1]; kp.a[j] = kp.a[j + 1]; kp.r[j] = kp.r[j + 1]; kp.i[j] = kp.i[j + 1]; }
            }
            const uint32_t h1 = an.v[2], h2 = an.v[3], h256 = an.v[4], h512 = an.v[5], h1024 = an.v[6];
            cpair p[11];
            p[0] = {an.v[0], an.v[1]};
            p[1] = pmul(p[0], h2); p[2] = pmul(p[0], h1); p[3] = pmul(p[1], h1);
            p[4] = pmul(p[0], h256); p[5] = pmul(p[1], h256); p[6] = pmul(p[0], h512); p[7] = pmul(p[4], h512);
            p[8] = pmul({__byte_perm(p[0].r, p[4].r, 0x5410), __byte_perm(p[0].i, p[4].i, 0x5410)}, h1024);
            p[9] = pmul(p[8], h512); p[10] = pmul(p[8], h1024);
#pragma unroll
            for (int j = 0; j < 3; j++) {
                const uint32_t a = tb + 8192 + (((3 * half + j) ^ sw) << 4);
                sts128(a, make_uint4(p[4 * j].r, p[4 * j + 1].r, p[4 * j + 2].r, p[j < 2 ? 4 * j + 3 : 10].r));
                sts128(a + 4096, make_uint4(p[4 * j].i, p[4 * j + 1].i, p[4 * j + 2].i, p[j < 2 ? 4 * j + 3 : 10].i));
            }
            an = kg_anchor_hi(kp, sel, dt, cs);
        }
        if (c == 0) TS(24);
        if (c == 3) TS(25);
        fence_async_smem();
        wg_wait<0>();
        named_bar(5 + wg, 128);
        wg_fence();
#pragma unroll
        for (int k = 0; k < 4; k++) wgmma_kg(acc, da + k * 128, da + 512 + k * 128, 1);
        wg_commit();
        tb += flip; da += flip >> 4; flip = -flip;
    }
    const bool up = warp & 2;
    const int r = 2 * wg + up, lo0 = 16 * half + (lane >> 2);
    const uint32_t o = dump + r * KG_RES + lo0 * 52 + 4 * (lane & 3);
    const float ci = __uint_as_float(lds32(s2u(&ks->cinv[r])));
    const float ds = (lane == 0 && warp <= 8 && !half) ? bf_lo(kp.ds) : 0.f;
    TS(26);
    wg_wait<0>();
    float v[12], m = 0.f;
#pragma unroll
    for (int j = 0; j < 12; j++) { v[j] = fmaf(ci, up ? acc[12 + j] : acc[j], j ? 0.f : ds); m = fmaxf(m, fabsf(v[j])); }
    const uint32_t mm = __reduce_max_sync(~0u, __float_as_uint(m));
    if (lane == 0) asm volatile("red.shared.max.u32 [%0], %1;" ::"r"(s2u(&ks->kmax[r])), "r"(mm) : "memory");
    named_bar(5 + wg, 128);
    const float mx = __uint_as_float(lds32(s2u(&ks->kmax[r]))) + (wg == 2 ? __uint_as_float(lds32(s2u(&ks->kmax[r ^ 1]))) : 0.f);
    const uint32_t e = min(max(__float_as_uint(mx) >> 23, 4u), 250u);
    const float sc = __uint_as_float((253u - e) << 23);
    if (lane == 0) ks->kexp[r] = e;
#pragma unroll
    for (int j = 0; j < 6; j++) sts32(o + (j & 1) * 416 + (j >> 1) * 16, pack2h(v[2 * j] * sc, v[2 * j + 1] * sc));
}
#define F_WEAK 0
#define F_STAG 4
#define F_SHARE 1
__device__ __forceinline__ void wgmma_h64_rs(uint32_t (&d)[16], const uint4& a, uint64_t db, int scale_d) {
    asm volatile("{\n.reg .pred p;\nsetp.ne.b32 p, %21, 0;\n"
                 "wgmma.mma_async.sync.aligned.m64n64k16.f16.f16.f16 {%0,%1,%2,%3,%4,%5,%6,%7,%8,%9,%10,%11,%12,%13,%14,%15}, {%16,%17,%18,%19}, %20, p, 1, 1, 1;\n}\n"
                 : "+r"(d[0]), "+r"(d[1]), "+r"(d[2]), "+r"(d[3]), "+r"(d[4]), "+r"(d[5]), "+r"(d[6]), "+r"(d[7]), "+r"(d[8]), "+r"(d[9]),
                   "+r"(d[10]), "+r"(d[11]), "+r"(d[12]), "+r"(d[13]), "+r"(d[14]), "+r"(d[15])
                 : "r"(a.x), "r"(a.y), "r"(a.z), "r"(a.w), "l"(db), "r"(scale_d));
}
template <int TB>
__device__ __forceinline__ void wgmma_h32_rs(uint32_t (&d)[8], const uint4& a, uint64_t db, int scale_d) {
    asm volatile("{\n.reg .pred p;\nsetp.ne.b32 p, %13, 0;\n"
                 "wgmma.mma_async.sync.aligned.m64n32k16.f16.f16.f16 {%0,%1,%2,%3,%4,%5,%6,%7}, {%8,%9,%10,%11}, %12, p, 1, 1, %14;\n}\n"
                 : "+r"(d[0]), "+r"(d[1]), "+r"(d[2]), "+r"(d[3]), "+r"(d[4]), "+r"(d[5]), "+r"(d[6]), "+r"(d[7])
                 : "r"(a.x), "r"(a.y), "r"(a.z), "r"(a.w), "l"(db), "r"(scale_d), "n"(TB));
}
__device__ __forceinline__ void wgmma_s1(uint32_t (&d)[16], const uint4& a, uint64_t db, int scale_d) { wgmma_h64_rs(d, a, db, scale_d); }
__device__ __forceinline__ void wgmma_s1(uint32_t (&d)[8], const uint4& a, uint64_t db, int scale_d) { wgmma_h32_rs<1>(d, a, db, scale_d); }
__device__ __forceinline__ void wgmma_s4(float (&d)[32], const uint4& a, uint64_t db, uint32_t meta, int scale_d) {
    asm volatile("{\n.reg .pred p;\nsetp.ne.b32 p, %38, 0;\n"
                 "wgmma.mma_async.sp.sync.aligned.m64n64k32.f32.f16.f16 {%0,%1,%2,%3,%4,%5,%6,%7,%8,%9,%10,%11,%12,%13,%14,%15,%16,%17,%18,%19,%20,%21,%22,%23,%24,%25,%26,%27,%28,%29,%30,%31}, {%32,%33,%34,%35}, %36, %37, 0, p, 1, 1, 1;\n}\n"
                 : "+f"(d[0]), "+f"(d[1]), "+f"(d[2]), "+f"(d[3]), "+f"(d[4]), "+f"(d[5]), "+f"(d[6]), "+f"(d[7]), "+f"(d[8]), "+f"(d[9]), "+f"(d[10]), "+f"(d[11]), "+f"(d[12]), "+f"(d[13]), "+f"(d[14]), "+f"(d[15]), "+f"(d[16]), "+f"(d[17]), "+f"(d[18]), "+f"(d[19]), "+f"(d[20]), "+f"(d[21]), "+f"(d[22]), "+f"(d[23]), "+f"(d[24]), "+f"(d[25]), "+f"(d[26]), "+f"(d[27]), "+f"(d[28]), "+f"(d[29]), "+f"(d[30]), "+f"(d[31])
                 : "r"(a.x), "r"(a.y), "r"(a.z), "r"(a.w), "l"(db), "r"(meta), "r"(scale_d));
}
__device__ __forceinline__ void wgmma_s4(float (&d)[16], const uint4& a, uint64_t db, uint32_t meta, int scale_d) {
    asm volatile("{\n.reg .pred p;\nsetp.ne.b32 p, %22, 0;\n"
                 "wgmma.mma_async.sp.sync.aligned.m64n32k32.f32.f16.f16 {%0,%1,%2,%3,%4,%5,%6,%7,%8,%9,%10,%11,%12,%13,%14,%15}, {%16,%17,%18,%19}, %20, %21, 0, p, 1, 1, 1;\n}\n"
                 : "+f"(d[0]), "+f"(d[1]), "+f"(d[2]), "+f"(d[3]), "+f"(d[4]), "+f"(d[5]), "+f"(d[6]), "+f"(d[7]), "+f"(d[8]), "+f"(d[9]), "+f"(d[10]), "+f"(d[11]), "+f"(d[12]), "+f"(d[13]), "+f"(d[14]), "+f"(d[15])
                 : "r"(a.x), "r"(a.y), "r"(a.z), "r"(a.w), "l"(db), "r"(meta), "r"(scale_d));
}

__device__ __forceinline__ uint32_t& u4r(uint4& v, int i) { return i == 0 ? v.x : i == 1 ? v.y : i == 2 ? v.z : v.w; }

template <int NC>
__device__ __forceinline__ void fft_stage(const uint32_t (&u)[2][4], int c, uint32_t eo, int w, int lane) {
    const int mi = lane >> 3, mj = lane & 7;
    const uint32_t a = eo + (8 * w + mj) * 128 + (((4 * c + mi) ^ mj) << 4);
    stsm_x4(a, hadd(u[0][0], u[1][0]), hadd(u[0][1], u[1][1]), hadd(u[0][2], u[1][2]), hadd(u[0][3], u[1][3]));
    stsm_x4(NC == 2 ? a + 4096 : a ^ 64, hsub(u[0][0], u[1][0]), hsub(u[0][1], u[1][1]), hsub(u[0][2], u[1][2]), hsub(u[0][3], u[1][3]));
}
template <int NC>
__device__ __forceinline__ void kernel_stage(const uint4 (&ko)[2], uint32_t kt, uint32_t eo, int w, int lane) {
    uint32_t u[2][2][4];
#pragma unroll
    for (int h = 0; h < 2; h++)
#pragma unroll
        for (int j = 0; j < 4; j++) {
            const uint32_t a0 = kt + (u4(ko[h], j) & 0xFFFF), a1 = kt + (u4(ko[h], j) >> 16);
#pragma unroll
            for (int c = 0; c < 2; c++)
                asm volatile("{\n.reg .b16 a, b;\nld.shared.b16 a, [%1];\nld.shared.b16 b, [%2];\nmov.b32 %0, {a, b};\n}"
                             : "=r"(u[c][h][j]) : "r"(a0 + c * KG_RES), "r"(a1 + c * KG_RES) : "memory");
            if (NC == 1) u[0][h][j] = hadd(u[0][h][j], u[1][h][j]);
        }
#pragma unroll
    for (int c = 0; c < NC; c++) fft_stage<NC>(u[c], c, eo, w, lane);
}

template <int NC, bool SHEAR, class Mid>
__device__ __forceinline__ void fft_forward(const uint4 (&a1)[4], const uint4 (&tw)[4], uint32_t eo, uint32_t s2, uint32_t (&X)[NC][2][8], Mid mid) {
    uint32_t dr[8 * NC], di[8 * NC];
    const uint64_t de = mkdesc(eo, 4096, 1024, 1), d2 = mkdesc(s2, 16, 1024, 1);
    wg_fence();
    wgmma_s1(dr, a1[0], de, 0);
    wgmma_s1(di, a1[2], de + (NC == 2 ? 256 : 4), 0);
    wgmma_s1(dr, a1[1], de + 128, 1);
    wgmma_s1(di, a1[3], de + (NC == 2 ? 384 : 132), 1);
    wg_commit();
    mid();
    wg_wait<0>();
#pragma unroll
    for (int c = 0; c < NC; c++) {
        uint4 zr[2], zi[2];
#pragma unroll
        for (int p = 0; p < 2; p++)
#pragma unroll
            for (int i = 0; i < 4; i++) {
                const uint32_t r = dr[8 * c + 4 * p + i], m = di[8 * c + 4 * p + i], tr = u4(tw[p], i), ti = u4(tw[2 + p], i);
                if (SHEAR) {
                    const uint32_t r1 = hfma(tr, m, r), m1 = hfma(ti, r1, m);
                    u4r(zr[p], i) = hfma(tr, m1, r1); u4r(zi[p], i) = m1;
                } else {
                    u4r(zr[p], i) = hfms(m, ti, hmul(r, tr));
                    u4r(zi[p], i) = hfma(m, tr, hmul(r, ti));
                }
            }
        wg_fence();
        wgmma_h32_rs<0>(X[c][0], zi[0], d2 + 2, 0);
        wgmma_h32_rs<0>(X[c][1], zi[1], d2 + 6, 0);
        wgmma_h32_rs<0>(X[c][0], zr[0], d2, 1);
        wgmma_h32_rs<0>(X[c][1], zr[1], d2 + 4, 1);
        wg_commit();
    }
}

template <int NC, class Mid, class Ready, class Asked, class Staged>
__device__ __forceinline__ void conv_wg(int ch0, int layer, uint32_t eo, uint32_t zb, uint32_t s23, uint32_t kexp, uint32_t st, uint32_t sbar,
                                        int warp, int lane, uint4 (&a1)[4], uint4 (&tw)[4], Mid mid, Ready ready, Asked asked, Staged staged TS_ARG) {
    const int wg = warp >> 2, w = warp & 3, t = 32 * w + lane, g = lane >> 2, q = lane & 3, mi = lane >> 3, mj = lane & 7;
    auto F = [](uint32_t x) { return __uint_as_float(x); };
    auto U = [](float x) { return __float_as_uint(x); };
    uint32_t KH[NC][2][8];
    TS(2);
    fft_forward<NC, false>(a1, tw, eo, s23, KH, mid);
    named_bar(1 + wg, 128);
    uint4 a4[4];
    if (NC == 2) {
#pragma unroll
        for (int i = 0; i < 4; i++) { tw[i] = ldg_tab(4 + i, t); a4[i] = ldg_tab(12 + i, t); }
    }
    wg_wait<0>();
    TS(4);
    ready();
    TS(5);
    uint2 x[NC][2][2];
    const int ra[2] = {16 * (8 * w + g) + 4 * q, 16 * (63 - 8 * w - g) + 4 * q};
    {
        uint4 s[2][2][2];
        constexpr bool own = NC == 1 || !F_SHARE;
#pragma unroll
        for (int h = 0; h < 2; h++)
#pragma unroll
            for (int p = 0; p < 2; p++) {
                if (own) { s[h][p][0] = ldg128(g_sums[layer][0] + 1024 * p + ra[h]); s[h][p][1] = ldg128(g_sums[layer][1] + 1024 * p + ra[h]); }
                if (NC == 2) {
#pragma unroll
                    for (int c = 0; c < NC; c++) x[c][h][p] = ldg64(g_x1T + (size_t)(ch0 + c) * XP + 1024 * p + ra[h]);
                }
            }
        asked();
        if (NC == 1) {
#pragma unroll
            for (int i = 0; i < 4; i++) x[0][i >> 1][i & 1] = ldg64(g_x1T + (size_t)ch0 * XP + 1024 * (i & 1) + ra[i >> 1]);
        }
        TS(6);
        if (own) {
#pragma unroll
            for (int hp = 0; hp < 4; hp++) {
                uint4 &a = s[hp >> 1][hp & 1][0], &b = s[hp >> 1][hp & 1][1];
#pragma unroll
                for (int i = 0; i < 4; i++) {
                    const float m = F(u4(a, i)) * (1.0f / DM), r = frsq(fmaxf(fmaf(F(u4(b, i)), 1.0f / DM, fmaf(-m, m, 1e-5f)), 1e-5f));
                    u4r(a, i) = U(r); u4r(b, i) = U(-m * r);
                }
                if (F_SHARE) { sts128(st + (2 * hp) * 2048 + t * 16, a); sts128(st + (2 * hp + 1) * 2048 + t * 16, b); }
            }
            if (F_SHARE) { __syncwarp(); if (lane == 0) mbar_arrive(sbar + 8 * w); }
        } else {
            mbar_wait(sbar + 8 * w, 0);
#pragma unroll
            for (int i = 0; i < 8; i++) s[i >> 2][(i >> 1) & 1][i & 1] = lds128(st + i * 2048 + t * 16);
        }
        if (F_STAG == 1 && NC == 2 && wg == 1) named_bar(10 + w, 64);
        TS(7);
#pragma unroll
        for (int c = 0; c < NC; c++) {
            uint32_t u[2][4];
#pragma unroll
            for (int h = 0; h < 2; h++)
#pragma unroll
                for (int j = 0; j < 4; j++) {
                    const uint4 &a = s[h][j >> 1][0], &b = s[h][j >> 1][1];
                    const uint32_t xv = (j & 1) ? x[c][h][j >> 1].y : x[c][h][j >> 1].x;
                    u[h][j] = pack2h(fmaf(bf_lo(xv), F(u4(a, 2 * (j & 1))), F(u4(b, 2 * (j & 1)))), fmaf(bf_hi(xv), F(u4(a, 2 * (j & 1) + 1)), F(u4(b, 2 * (j & 1) + 1))));
                }
            fft_stage<NC>(u, c, eo, w, lane);
        }
    }
    if (F_STAG == 1 && NC == 2 && wg == 0) asm volatile("bar.arrive %0, 64;" ::"r"(10 + w) : "memory");
    TS(8);
    fence_async_smem();
    TS(9);
    if (NC == 1) {
#pragma unroll
        for (int i = 0; i < 4; i++) { tw[i] = ldg_tab(4 + i, t); a4[i] = ldg_tab(12 + i, t); }
    }
    staged();
    named_bar(1 + wg, 128);
    uint32_t X[NC][2][8], Y[NC][2][8];
    fft_forward<NC, true>(a1, tw, eo, s23, X, [&] { TS(3); if (F_STAG >= 2 && NC == 2 && wg == 1) named_bar(10 + w, 64); });
    if (F_STAG == 2 && NC == 2 && wg == 0) asm volatile("bar.arrive %0, 64;" ::"r"(10 + w) : "memory");
    TS(10);
    const uint64_t d3 = mkdesc(s23 + 4096, 16, 1024, 1);
#pragma unroll
    for (int c = 0; c < NC; c++) {
        wg_wait<NC - 1>();
        TS(11 + c);
        uint4 pr[2], pi[2];
#pragma unroll
        for (int i = 0; i < 4; i++) {
            const uint32_t er = X[c][0][i], ei = X[c][0][4 + i], orr = X[c][1][i], oi = X[c][1][4 + i];
            const uint32_t ar = KH[c][0][i], ai = KH[c][0][4 + i], br = KH[c][1][i], bi = KH[c][1][4 + i];
            u4r(pr[0], i) = hfms(bi, oi, hfma(br, orr, hfms(ai, ei, hmul(ar, er))));
            u4r(pi[0], i) = hfma(bi, orr, hfma(br, oi, hfma(ai, er, hmul(ar, ei))));
            u4r(pr[1], i) = hfms(ai, oi, hfma(ar, orr, hfms(bi, ei, hmul(br, er))));
            u4r(pi[1], i) = hfma(ai, orr, hfma(ar, oi, hfma(bi, er, hmul(br, ei))));
        }
        if (F_STAG == 3 + c && NC == 2 && wg == 0) asm volatile("bar.arrive %0, 64;" ::"r"(10 + w), "r"(pr[0].x ^ pr[1].w ^ pi[0].y ^ pi[1].z) : "memory");
        wg_fence();
        wgmma_h32_rs<0>(Y[c][0], pr[0], d3, 0);
        wgmma_h32_rs<0>(Y[c][1], pr[1], d3 + 4, 0);
        wgmma_h32_rs<0>(Y[c][0], pi[0], d3 + 2, 1);
        wgmma_h32_rs<0>(Y[c][1], pi[1], d3 + 6, 1);
        wg_commit();
    }
#pragma unroll
    for (int c = 0; c < NC; c++) {
        if (c + 1 < NC) wg_wait<1>(); else wg_wait<0>();
        TS(13 + c);
        uint32_t zr[2][4], zi[2][4];
#pragma unroll
        for (int p = 0; p < 2; p++)
#pragma unroll
            for (int i = 0; i < 4; i++) {
                const uint32_t r = Y[c][p][i], m = Y[c][p][4 + i], tr = u4(tw[p], i), ti = u4(tw[2 + p], i);
                const uint32_t r1 = hfms(tr, m, r), m1 = hfms(ti, r1, m);
                zr[i & 1][2 * p + (i >> 1)] = hfms(tr, m1, r1);
                zi[i & 1][2 * p + (i >> 1)] = m1;
            }
        const int kr = 4 * (mj >> 1) + (mj & 1) + 2 * (mj >> 2), ki = kr ^ 2;
#pragma unroll
        for (int h = 0; h < 2; h++) {
            const uint32_t a = zb + (2 * w + h) * 2048;
            stsm_x4(a + ki * 128 + (((4 * c + mi) ^ (ki & 7)) << 4), zi[h][0], zi[h][1], zi[h][2], zi[h][3]);
            stsm_x4(a + kr * 128 + (((4 * c + mi) ^ (kr & 7)) << 4), zr[h][0], zr[h][1], zr[h][2], zr[h][3]);
        }
    }
    TS(15);
    fence_async_smem();
    TS(16);
    named_bar(1 + wg, 128);
    TS(17);
    float acc[16 * NC];
    const uint64_t dz = mkdesc(zb, 4096, 1024, 1);
    wg_fence();
#pragma unroll
    for (int ks = 0; ks < 4; ks++) wgmma_s4(acc, a4[ks], dz + ks * 256, 0x44EEEE44u, ks > 0);
    wg_commit();
    uint32_t oscale[NC];
#pragma unroll
    for (int c = 0; c < NC; c++) oscale[c] = (lds32(kexp + 4 * c) + 3u) * 0x00800080u;
    bf16* dst = g_x2T[layer] + (size_t)ch0 * XP;
    wg_wait<0>();
    TS(18);
#pragma unroll
    for (int c = 0; c < NC; c++)
#pragma unroll
        for (int p = 0; p < 2; p++) {
            uint32_t r[2][2];
#pragma unroll
            for (int j = 0; j < 2; j++) {
                const float* d = acc + 4 * (4 * c + 2 * p + j);
                const uint32_t y0 = pack2(d[0] + d[2], d[1] + d[3]), y1 = pack2(d[0] - d[2], d[1] - d[3]);
                asm("fma.rn.bf16x2 %0, %1, %2, %3;" : "=r"(r[0][j]) : "r"(y0), "r"(oscale[c]), "r"(j ? x[c][0][p].y : x[c][0][p].x));
                asm("fma.rn.bf16x2 %0, %1, %2, %3;" : "=r"(r[1][j]) : "r"(y1), "r"(oscale[c]), "r"(j ? x[c][1][p].y : x[c][1][p].x));
            }
#pragma unroll
            for (int h = 0; h < 2; h++)
                if (F_WEAK) *(uint2*)(dst + c * XP + 1024 * p + ra[h]) = make_uint2(r[h][0] ? r[h][0] : 0x80000000u, r[h][1]);
                else st_ll((unsigned long long*)(dst + c * XP + 1024 * p + ra[h]), r[h][0] ? r[h][0] : 0x80000000u, r[h][1]);
        }
    TS(19);
}

#define Q_SCHED 3
#define Q_WAITFOR(it) (Q_SCHED == 0 ? (it) - 2 : Q_SCHED == 1 ? ((it) == 3 ? 1 : 0) : Q_SCHED == 2 ? -1 : (it) - 1)
#define Q_S0 8
#define Q_WGATE 0
#define Q_ROT 0
#define O_ROT 0
#define O_MASK 127u
#define O_DEPTH 3
#define O_GATE 0
#define A_HPOS 1
#define A_CSPRE 2
#define O_RING 1
#define R_CONS 200
#define F_PRE 4
#define FIN_DELAY 500
#define T_PF 1
#define K_CSUN 1
constexpr int K_CSU = K_CSUN;
#define G_MAP 1
#define FIN_SLEEP 0
constexpr int Q_ST = 4;
constexpr int Q_AB = 16384, Q_BB = 30720, Q_SB = Q_AB + Q_BB;
constexpr int Q_EROW = 336;
constexpr int Q_ESLOT = 8 * Q_EROW;
constexpr int Q_EOFF = Q_ST * Q_SB;
constexpr int Q_KG = 2 * Q_SB;
static_assert(3 * Q_ESLOT <= 8192 && Q_KG + KG_TABLES <= Q_EOFF + 4096, "exchange slots, kernel generation");
constexpr int F_EO = Q_EOFF, F_S23 = F_EO + 2 * 8192 + 4096, Q_KDUMP = F_S23 + 8192;
constexpr int Q_SMEM = Q_KDUMP + 6 * KG_RES + TS_SMEM;
__host__ __device__ constexpr int w_grp(int j) { return j < 7 ? 2 * Q_SB + j * 12800 : 20480; }
constexpr int W_RES = 0, W_OUT = Q_SB;

constexpr int Q_ZERO = Q_EOFF + 4096, Q_WOT = Q_EOFF + 8320;

__device__ unsigned g_epoch;
__device__ __align__(1024) unsigned g_bar[4][16][32];
__device__ __align__(1024) uint4 g_wop[8][80][10][8];
__device__ __align__(1024) uint4 g_csp[8][16][96];
__device__ __align__(1024) uint4 g_stp[16][8][64];
__device__ __align__(1024) uint4 g_halo[128][2][5][32];
__device__ __align__(1024) uint4 g_of[8][16][8][5][32];

struct Bars { uint64_t full[Q_ST], empty[Q_ST], wfull[3], ex[7], res, go, qdone, prep, ardy, hdone, fdone, idx, att1, st[4], kfree; };
constexpr int NBAR = sizeof(Bars) / 8;
__host__ __device__ constexpr int bar_count(int i) {
#define BAR_IS(f) (i == offsetof(Bars, f) / 8)
    return (i >= 4 && i < 8) ? 16 : (BAR_IS(go) || BAR_IS(att1) || BAR_IS(ardy)) ? 4 : BAR_IS(qdone) ? 8 : BAR_IS(prep) ? 96 :
           BAR_IS(hdone) ? 6 : BAR_IS(fdone) ? 3 : BAR_IS(kfree) ? 24 : 1;
}
__device__ __forceinline__ void grid_wait(const unsigned* c, int n, unsigned target, int lane) {
    const unsigned* p = c + 32 * min(lane, n - 1);
    unsigned v;
    int spin = 0;
    do { asm volatile("ld.relaxed.gpu.global.u32 %0, [%1];" : "=r"(v) : "l"(p) : "memory"); } while (!__all_sync(~0u, (int)(v - target) >= 0) && ++spin < (1 << 18));
    fence_acquire();
}
__device__ __forceinline__ void grid_arrive(unsigned* c) {
    fence_release();
    asm volatile("red.relaxed.gpu.global.add.u32 [%0], 1;" ::"l"(c) : "memory");
}

#define TMAP(n) ([] { const CUtensorMap* p_; asm volatile("{\n.reg .b64 t;\nmov.b64 t, fused_kernel_param_" #n ";\ncvta.param.u64 %0, t;\n}" : "=l"(p_)); return p_; }())
extern "C" __global__ void __launch_bounds__(384, 1)
fused_kernel(const SsmParams sp, const __grid_constant__ CUtensorMap mX0, const __grid_constant__ CUtensorMap mX1, const __grid_constant__ CUtensorMap mW,
             const __grid_constant__ CUtensorMap mWr,
             const __grid_constant__ CUtensorMap mRes0, const __grid_constant__ CUtensorMap mRes1, const __grid_constant__ CUtensorMap mOut,
             const __grid_constant__ CUtensorMap mWo, const __grid_constant__ CUtensorMap mFin) {
    extern __shared__ __align__(1024) char smraw[];
    __shared__ __align__(8) Bars s_bar[2];
    __shared__ __align__(16) float s_cs[240], s_mean[2][64], s_rstd[2][72];
    __shared__ KgShared s_kg;
    __shared__ uint32_t s_epoch;
    const uint32_t sb = s2u(smraw);
    int tid, warp, lane, bx, rank, blk, hg, rot, c0;
    int role;
    {
        const int c = blockIdx.x >> 1, d = c - 41, r = d >= 21 ? 3 : d >= 14 ? 2 : d >= 7 ? 1 : 0;
        const int gp = c < 4 ? 0 : c <= 40 ? (c + 7) & 7 : d - 7 * r + 1;
        const int k = c < 4 ? c : c <= 40 ? (c >> 3) + (gp == 0 ? 3 : gp >= 3 && gp < 7 ? 0 : -1) : (gp >= 3 ? 5 : 4) + r;
        role = G_MAP == 1 ? 16 * k + 2 * gp + (blockIdx.x & 1) : G_MAP == 2 ? 16 * gp + 2 * k + (blockIdx.x & 1) : blockIdx.x;
    }
    auto indices = [&] {
        asm volatile("mov.u32 %0, %%tid.x;" : "=r"(tid));
        asm volatile("mov.u32 %0, %1;" : "=r"(bx) : "r"(role));
        warp = __shfl_sync(~0u, tid >> 5, 0); lane = tid & 31;
        rank = bx & 1; blk = bx & 15; hg = bx >> 4;
        const int u = ((blk >> 1) + hg) & 7;
        rot = (5 * u) >> 2; c0 = 16 * (u & 3);
    };
    indices();
    TS_DECL;
    TS_BEGIN;
#define EPOCH lds32(s2u(&s_epoch))
    int layer = 0;
    uint32_t bars = s2u(s_bar);
#define BAR(f) (bars + (uint32_t)offsetof(Bars, f))
    auto chunk = [&](int it) { return Q_ROT ? it + rot - (it + rot >= 10 ? 10 : 0) : it < 2 ? rot + it : it - 2 < rot ? it - 2 : it; };
    auto osrc_of = [&](int j) { return O_ROT ? (hg + j) & 7 : j == 0 ? hg : j - 1 < hg ? j - 1 : j; };
    auto issue_w = [&](uint32_t bb, int it, int half) {
        const int s = it & (Q_ST - 1);
        const uint32_t fb = bb + 8 * s, db = sb + s * Q_SB + Q_AB + half * 15360;
        const int k0 = chunk(it) * 64 + half * 32;
#pragma unroll
        for (int p = 0; p < 3; p++) tma2d_mc(db + p * 4096, TMAP(3), p * DM + hg * 80, k0, fb, 3);
        tma3d_mc(db + 12288, TMAP(4), hg * 80 + 64, k0, 0, fb, 3);
    };
    auto issue_x = [&](int it) {
        const int s = it & (Q_ST - 1), kc = chunk(it);
        mbar_expect(BAR(full) + 8 * s, Q_SB);
        tma3d(sb + s * Q_SB, TMAP(1) + layer, (layer ? blk : kc) * 64, (layer ? kc : blk) * 64, 0, BAR(full) + 8 * s);
    };
    auto clear_fin = [&](uint32_t zero) {
#pragma unroll 1
        for (int i = 0; i < 5; i++) bulk_s2g(g_x2T[1] + (bx * 5 + i) * XP, zero, SEQ * 2);
        bulk_commit();
    };
    {
        KgParams kp;
        kgen_load(kp, bx * 5, warp, lane, sp);
        if (warp < 8) {
            cluster_arrive_relaxed();
        } else {
            const int t2 = tid - 256;
            if (elect_one()) {
                if (warp < 10) { prefetch_tmap(TMAP(3)); prefetch_tmap(TMAP(4)); } else prefetch_tmap(warp == 10 ? TMAP(1) : TMAP(8));
                const uint32_t b0 = bars + (warp >= 10 ? sizeof(Bars) : 0);
                if (warp & 1) {
#pragma unroll
                    for (int i = 0; i < NBAR / 2; i++) mbar_init(b0 + i * 8, bar_count(i));
                } else {
#pragma unroll
                    for (int i = NBAR / 2; i < NBAR; i++) mbar_init(b0 + i * 8, bar_count(i));
                }
                fence_mbar_init();
            }
            __syncwarp();
            cluster_arrive_relaxed();
            TS(29);
            const uint32_t epoch0 = ldg32(&g_epoch);
            sts128(sb + Q_ZERO + t2 * 16, make_uint4(0, 0, 0, 0)); sts128(sb + Q_ZERO + 2048 + t2 * 16, make_uint4(0, 0, 0, 0));
            cluster_wait();
            TS(27);
            if (elect_one()) {
                if (warp < 10) {
                    issue_w(BAR(full), warp - 8, rank);
                } else if (warp == 10) {
                    issue_x(0); issue_x(1);
                    prefetch_l2((const char*)c_fft + bx * (sizeof(c_fft) / 128), sizeof(c_fft) / 128);
                } else {
                    mbar_expect(BAR(idx), 8192 + 6400);
                    asm volatile("cp.async.bulk.tensor.4d.shared::cluster.global.mbarrier::complete_tx::bytes [%0], [%1, {0, 0, %3, %4}], [%2];"
                                 ::"r"(sb + Q_WOT), "l"(TMAP(8)), "r"(BAR(idx)), "r"(10 * hg), "r"(5 * blk) : "memory");
                    bulk_g2s(sb + F_S23, c_fft + 18 * 512, 8192, BAR(idx));
                }
            }
            __syncwarp();
            if (t2 == 0) s_epoch = epoch0;
            TS(30);
        }
        indices();
        kgen_tables(kp, sb + Q_KG, sb + Q_KDUMP, &s_kg, warp, lane TS_PASS);
        if (warp < 8) cluster_wait();
        __syncwarp();
        if (lane == 0) { mbar_arrive_cta(BAR(kfree), 0); mbar_arrive_cta(BAR(kfree), 1); }
        if (warp >= 8) {
            const int t2 = tid - 256;
            float csum[10];
            if (warp == 11 && elect_one()) clear_fin(sb + Q_ZERO);
            __syncwarp();
            if (t2 < 64) g_sums[0][0][64 * bx + t2] = 0.f;
#pragma unroll
            for (int i = 0; i < 3; i++)
                if (t2 + 128 * i < 320) stg128(&g_halo[bx][0][0][0] + t2 + 128 * i, make_uint4(0, 0, 0, 0));
            if (warp == 8) asm volatile("bar.arrive 13, 128;" ::: "memory"); else named_bar(13, 128);
            if (warp > 8) {
                const int hw = warp - 9, mi = lane >> 3, mj = lane & 7;
                mbar_wait(BAR(idx), 0);
                if (hw == 2 && elect_one()) { bulk_s2g(&g_wop[hg][5 * blk], sb + Q_WOT, 6400); bulk_commit(); }
                __syncwarp();
                mbar_wait(BAR(full), 0);
                mbar_wait(BAR(full) + 8, 0);
#pragma unroll
                for (int f = 0; f < 10; f++) csum[f] = 0.f;
#pragma unroll K_CSU
                for (int G = 0; G < 5; G++) {
                    const int row = c0 + 40 * rank + 8 * G + mj;
                    const uint32_t b = sb + (row >> 6) * Q_SB + Q_AB + ((row >> 5) & 1) * 15360;
                    uint32_t r[10];
                    ldsm_x4_t(r[0], r[1], r[2], r[3], b + hw * 4096 + (row & 31) * 128 + ((mi ^ mj) << 4));
                    ldsm_x4_t(r[4], r[5], r[6], r[7], b + hw * 4096 + (row & 31) * 128 + (((4 + mi) ^ mj) << 4));
                    ldsm_x2_t(r[8], r[9], b + 12288 + hw * 1024 + (row & 31) * 32 + (((mi & 1) ^ (mj >> 2)) << 4));
#pragma unroll
                    for (int f = 0; f < 10; f++) csum[f] += bf_lo(r[f]) + bf_hi(r[f]);
                }
                const int q = lane & 3;
                float t[3];
#pragma unroll
                for (int j = 0; j < 3; j++) {
                    float v[4];
#pragma unroll
                    for (int k = 0; k < 4; k++) v[k] = 4 * j + k < 10 ? csum[4 * j + k] : 0.f;
                    const float a0 = ((q & 2) ? v[2] : v[0]) + __shfl_xor_sync(~0u, (q & 2) ? v[0] : v[2], 2);
                    const float a1 = ((q & 2) ? v[3] : v[1]) + __shfl_xor_sync(~0u, (q & 2) ? v[1] : v[3], 2);
                    t[j] = ((q & 1) ? a1 : a0) + __shfl_xor_sync(~0u, (q & 1) ? a0 : a1, 1);
                }
                st_ll4(&g_csp[hg][blk][tid - 288], ~EPOCH & 1u, __float_as_uint(t[0]), __float_as_uint(t[1]), __float_as_uint(t[2]));
            }
        }
        TS(1);
    }

    uint4 fa1[4], ftw[4];
    auto conv_tables = [&] {
#pragma unroll
        for (int i = 0; i < 4; i++) { fa1[i] = ldg_tab(i, tid & 127); ftw[i] = ldg_tab(8 + i, tid & 127); }
    };
    auto conv_done = [&] {
        if (layer == 0) {
            named_bar(1 + (warp >> 2), 128);
            if ((tid & 127) == 0) {
                mbar_arrive(BAR(fdone));
                grid_arrive(g_bar[2][hg]);
            }
            __syncwarp();
        }
        TS(20);
    };
    if (warp >= 8) {
    asm volatile("setmaxnreg.dec.sync.aligned.u32 %0;" ::"n"(504 - 2 * R_CONS));
#pragma unroll 1
    for (; layer < 2; layer++, bars += sizeof(Bars)) {
        indices();
        TS_PHASE(2 * layer);
        if (warp == 8) {
            if (layer) {
                grid_wait(g_bar[2][0], 8, 48 * (EPOCH + 1), lane);
                mbar_wait(BAR(fdone) - sizeof(Bars), 0);
                fence_async_global();
                TS(1);
            }
            if (elect_one()) {
#pragma unroll 1
                for (int it = layer ? 0 : 2; it < 10; it++) {
                    if (it >= Q_ST) mbar_wait(BAR(empty) + 8 * (it & (Q_ST - 1)), ((it >> 2) - 1) & 1);
                    else if (layer == 0) mbar_wait(BAR(kfree), 0);
                    else if (it > 0 && Q_WAITFOR(it) >= 0) mbar_wait(BAR(full) + 8 * Q_WAITFOR(it), 0);
                    if (it == Q_ST) mbar_wait(BAR(hdone), 0);
                    issue_x(it);
                    if (layer == 0 || it >= F_PRE) issue_w(BAR(full), it, rank);
                }
                if (T_PF) { prefetch_tmap(TMAP(5) + layer); prefetch_tmap(TMAP(7)); }
                if (layer == 0) { mbar_wait(BAR(prep), 0); fence_async_global(); }
#pragma unroll 1
                for (int j = 0; j < 8; j++) {
                    const int b = (j + 1) >> 2;
                    const uint32_t fb = BAR(wfull) + 8 * b;
                    if (j == 0 || j == 3 || j == 7) {
                        mbar_wait(BAR(empty) + 8 * ((2 + b) & 3), b < 2);
                        TS(11 + b);
                        mbar_expect(fb, (b == 0 ? 3 : b == 1 ? 4 : 1) * 12800);
                    }
                    bulk_g2s_mc(sb + w_grp(j) + rank * 6400, &g_wop[hg][osrc_of(j) * 10 + rank * 5], 6400, fb, 3);
                }
                mbar_expect(BAR(res), 20480);
                if (layer == 0) tma3d(sb + W_RES, TMAP(1), hg * 80, blk * 64, 0, BAR(res));
                tma3d(sb + W_RES + (layer ? 0 : 16384), TMAP(5) + layer, layer ? blk * 64 : hg * 80 + 64, layer ? hg * 80 : blk * 64, 0, BAR(res));
            }
            __syncwarp();
        } else {
            const int ht = tid - 288, hw = warp - 9, mi = lane >> 3, mj = lane & 7, g = lane >> 2, q = lane & 3;
            auto F = [](uint32_t x) { return __uint_as_float(x); };
            auto U = [](float x) { return __float_as_uint(x); };
            const uint32_t lb = layer ^ 1, eb = ~EPOCH & 1u;
            mbar_wait(BAR(full), 0);
            mbar_wait(BAR(full) + 8, 0);
            if (ht == 0) TSX(2, 2);
            uint32_t xf[3][20];
#pragma unroll
            for (int i = 0; i < 3; i++) {
                const int tile = min(hw + 3 * i, 7);
#pragma unroll
                for (int k = 0; k < 5; k++) {
                    const int ch = c0 + 16 * k + 8 * (mi >> 1), tok = 16 * (tile & 3) + 8 * (mi & 1);
                    const uint32_t a = sb + (ch >> 6) * Q_SB + (tile >> 2) * 8192;
                    if (layer == 0) ldsm_x4(xf[i][4 * k], xf[i][4 * k + 1], xf[i][4 * k + 2], xf[i][4 * k + 3], a + (tok + mj) * 128 + ((((ch & 63) >> 3) ^ mj) << 4));
                    else ldsm_x4_t(xf[i][4 * k], xf[i][4 * k + 1], xf[i][4 * k + 2], xf[i][4 * k + 3], a + ((ch & 63) + mj) * 128 + (((tok >> 3) ^ mj) << 4));
                }
            }
            fence_async_smem();
            __syncwarp();
            if (lane == 0) { mbar_arrive_cta(BAR(hdone), 0); mbar_arrive_cta(BAR(hdone), 1); }
            if (ht == 0) TSX(2, 3);
            if (layer == 0) {
                if (hw == 2 && elect_one()) { bulk_wait(); fence_async_global(); grid_arrive(g_bar[3][hg]); }
                __syncwarp();
                mbar_wait(BAR(kfree), 0);
            }
            if (ht == 0) TSX(2, 8);
#pragma unroll 1
            for (int tile = hw; tile < 8; tile += 3) {
                float a[4] = {0.f, 0.f, 0.f, 0.f};
#pragma unroll
                for (int j = 0; j < 20; j++) {
                    const float lo = bf_lo(xf[0][j]), hi = bf_hi(xf[0][j]);
                    a[2 * (j & 1)] += lo + hi; a[2 * (j & 1) + 1] = fmaf(lo, lo, fmaf(hi, hi, a[2 * (j & 1) + 1]));
                    xf[0][j] = xf[1][j]; xf[1][j] = xf[2][j];
                }
#pragma unroll
                for (int j = 0; j < 4; j++) { a[j] += __shfl_xor_sync(~0u, a[j], 1); a[j] += __shfl_xor_sync(~0u, a[j], 2); }
                if (q == 0) st_ll4(&g_stp[blk][hg][8 * tile + g], (U(a[0]) & ~1u) | lb, U(a[1]), U(a[2]), U(a[3]));
            }
            if (ht == 0) TSX(2, 4);
            if (layer == 0) {
                float t[4] = {0.f, 0.f, 0.f, 0.f};
                uint4 v[16];
                int spin = 0;
                uint32_t bad;
                do {
                    bad = 0;
#pragma unroll
                    for (int j = 0; j < 16; j++) v[j] = ld_ll4(&g_csp[hg][j][ht]);
#pragma unroll
                    for (int j = 0; j < 16; j++) bad |= v[j].x ^ eb;
                } while ((bad & 1u) && ++spin < (1 << 18));
#pragma unroll
                for (int j = 0; j < 16; j++) { t[0] += F(v[j].y); t[1] += F(v[j].z); t[2] += F(v[j].w); }
#pragma unroll
                for (int j = 0; j < 3; j++) if (q + 4 * j < 10) s_cs[80 * hw + 20 * (g >> 1) + 2 * (q + 4 * j) + (g & 1)] = t[j];
                if (hw == 2) grid_wait(g_bar[3][0], 8, 16 * (EPOCH + 1), lane);
            }
            if (ht == 0) TSX(2, 15);
            if (ht < 80) {
                const bool halo = ht >= 64;
                const int p = halo ? (ht >> 3) & 1 : ht >> 5, i = halo ? (ht & 7) - 8 : 8 + 2 * (ht & 24) + (ht & 7);
                const uint4* src = &g_stp[halo && blk ? blk - 1 : blk][0][halo ? 32 * p + 24 + (ht & 7) : ht];
                uint4 v[8];
                int spin = 0;
                uint32_t bad;
                do {
                    bad = 0;
#pragma unroll
                    for (int j = 0; j < 8; j++) v[j] = ld_ll4(src + 64 * j);
#pragma unroll
                    for (int j = 0; j < 8; j++) bad |= v[j].x ^ lb;
                } while ((bad & 1u) && ++spin < (1 << 18));
                float t[4] = {0.f, 0.f, 0.f, 0.f};
#pragma unroll
                for (int j = 0; j < 8; j++) { t[0] += F(v[j].x); t[1] += F(v[j].y); t[2] += F(v[j].z); t[3] += F(v[j].w); }
                const uint32_t s0 = ln_finish_packed(t[0], t[1]), s1 = ln_finish_packed(t[2], t[3]);
                if (!halo) { s_mean[p][i - 8] = bf_hi(s0); s_mean[p][i] = bf_hi(s1); s_rstd[p][i] = frcp(bf_lo(s0)); }
                s_rstd[p][i + 8] = frcp(bf_lo(s1));
            }
            fence_acquire();
            mbar_arrive(BAR(prep));
            if (ht == 0) TSX(2, 5);
        }
        __syncwarp();
        TS_PHASE(2 * layer + 1);
        TS(0);
        indices();
        {
            const uint4 ko[2] = {ldg_tab(16, tid & 127), ldg_tab(17, tid & 127)};
            conv_tables();
            mbar_wait(BAR(att1), 0);
            kernel_stage<1>(ko, sb + Q_KDUMP + 4 * KG_RES, sb + F_EO + 2 * 8192, warp & 3, lane);
            fence_async_smem();
            named_bar(3, 128);
        }
        conv_wg<1>(5 * bx + 4, layer, sb + F_EO + 2 * 8192, sb + 2 * Q_SB, sb + F_S23, s2u(&s_kg.kexp[4]), sb + 3 * Q_SB, BAR(st), warp, lane, fa1, ftw,
        [] {}, [&] {
            if (warp == 8) {
                grid_wait(g_bar[layer][0], 8, 32 * (EPOCH + 1), lane);
                if (!F_SHARE && lane < 4) mbar_arrive(BAR(ardy));
            }
            if (F_SHARE) named_bar(3, 128); else mbar_wait(BAR(ardy), 0);
        }, [&] {
            if (F_SHARE && lane == 0) mbar_arrive(BAR(ardy));
        }, [&] {
            if (T_PF && tid == 352) prefetch_tmap(layer ? TMAP(9) : TMAP(2));
            if (layer == 0 && warp - 8 < F_PRE && elect_one()) issue_w(BAR(full) + sizeof(Bars), warp - 8, rank);
            __syncwarp();
        } TS_PASS);
        conv_done();
    }
    } else {
#pragma unroll 1
    for (; layer < 2; layer++, bars += sizeof(Bars)) {
    indices();
    TS_PHASE(2 * layer);
    const int wg = warp >> 2, w = warp & 3;
    const int mi = lane >> 3, mj = lane & 7, g = lane >> 2, q = lane & 3;
    TS(2);
    float acc[120];
#pragma unroll
    for (int i = 0; i < 120; i++) acc[i] = 0.f;
    auto release = [&](int it) {
        if (lane == 0) { mbar_arrive_cta(BAR(empty) + 8 * (it & (Q_ST - 1)), 0); mbar_arrive_cta(BAR(empty) + 8 * (it & (Q_ST - 1)), 1); }
    };
#pragma unroll 1
    for (int it = 0; it < 10; it++) {
        const int s = it & (Q_ST - 1);
        const uint32_t st = sb + s * Q_SB;
        const bool hold = wg == 1 && it == Q_S0;
        if (hold) {
            wg_wait<0>();
            release(it - 1);
            mbar_wait(BAR(go), 0);
        }
        mbar_wait(BAR(full) + 8 * (s), (it >> 2) & 1);
        if (it < 2) TS(3 + it);
        if (it == 6) TS(5);
        if (it == 9) TS(6);
        const uint64_t da = mkdesc(st + wg * 8192, 16, 1024, 1);
        const uint64_t db = mkdesc(st + Q_AB, 4096, 1024, 1);
        const uint64_t dr = mkdesc(st + Q_AB + 12288, 1024, 256, 3);
        if (layer == 0) {
            wg_fence();
#pragma unroll
            for (int ks = 0; ks < 4; ks++) {
                const int sc = 1;
                wgmma_n192<0, 1>(*(float(*)[96]) & acc[0], da + ks * 2, db + (ks >> 1) * 960 + (ks & 1) * 128, sc);
                wgmma_n48<0, 1>(*(float(*)[24]) & acc[96], da + ks * 2, dr + (ks >> 1) * 960 + (ks & 1) * 32, sc);
            }
            wg_commit();
        } else {
            wg_fence();
#pragma unroll
            for (int ks = 0; ks < 4; ks++) {
                const int sc = 1;
                wgmma_n192<1, 1>(*(float(*)[96]) & acc[0], da + ks * 128, db + (ks >> 1) * 960 + (ks & 1) * 128, sc);
                wgmma_n48<1, 1>(*(float(*)[24]) & acc[96], da + ks * 128, dr + (ks >> 1) * 960 + (ks & 1) * 32, sc);
            }
            wg_commit();
        }
        wg_wait<1>();
        if (it > 0 && !hold) release(it - 1);
    }
    if (wg == 0 && lane == 0) mbar_arrive(BAR(go));
    asm volatile("setmaxnreg.inc.sync.aligned.u32 %0;" ::"n"(R_CONS));
    mbar_wait(BAR(prep), 0);
    const uint32_t ob = layer ^ 1;
    const bool first = (blk == 0 && w == 0);
    const bool sel0 = (2 * q > g), sel1 = (2 * q + 1 > g);
    constexpr float SC = 0.22360679774997896f * 1.4426950408889634f;
    const float m0 = s_mean[wg][16 * w + g], m1 = s_mean[wg][8 + 16 * w + g];
    uint4 cs[3][5];
    auto cs_load = [&](int p) {
#pragma unroll
        for (int i = 0; i < 5; i++) cs[p][i] = lds128(s2u(&s_cs[80 * p + 20 * q + 4 * i]));
    };
    if (A_CSPRE >= 1) cs_load(1);
    if (A_CSPRE >= 2) cs_load(2);
    wg_wait<0>();
    if (A_CSPRE < 1) cs_load(1);
    if (A_CSPRE < 2) cs_load(2);
    TS(7);
    if (lane == 0) mbar_arrive(BAR(qdone));
    uint32_t ql[10], qh[10], kl[10], kh[10], vl[10], vh[10];
    auto fold = [&](int p, int f, int h) {
        const int j = (f < 8) ? 8 * p + f : 24 + 2 * p + (f - 8);
        const float c0 = __uint_as_float(u4(cs[p][f >> 1], 2 * (f & 1))), c1 = __uint_as_float(u4(cs[p][f >> 1], 2 * (f & 1) + 1));
        const float m = h ? m1 : m0;
        return pack2(fmaf(-m, c0, acc[4 * j + 2 * h]), fmaf(-m, c1, acc[4 * j + 2 * h + 1]));
    };
#pragma unroll
    for (int f = 0; f < 10; f++) { kh[f] = fold(1, f, 1); vh[f] = fold(2, f, 1); }
    if (w == 3) {
        uint4* hp = &g_halo[bx][wg][0][lane];
        st_ll4(hp, (kh[0] & ~1u) | ob, kh[1], kh[3], kh[4]); st_ll4(hp + 32, (kh[5] & ~1u) | ob, kh[6], kh[8], kh[9]);
        st_ll4(hp + 64, (vh[0] & ~1u) | ob, vh[1], vh[2], vh[3]); st_ll4(hp + 96, (vh[4] & ~1u) | ob, vh[5], vh[6], vh[7]);
        st_ll4(hp + 128, (vh[8] & ~1u) | ob, vh[9], kh[2], kh[7]);
    } else {
        const uint32_t a = sb + Q_EOFF + wg * 8192 + w * Q_ESLOT + mj * Q_EROW + mi * 16;
        stsm_x4(a, kh[0], kh[1], kh[3], kh[4]);
        stsm_x4(a + 64, kh[5], kh[6], kh[8], kh[9]);
        stsm_x4(a + 128, vh[0], vh[1], vh[2], vh[3]);
        stsm_x4(a + 192, vh[4], vh[5], vh[6], vh[7]);
        stsm_x4(a + 256, vh[8], vh[9], kh[2], kh[7]);
        __syncwarp();
        if (lane == 0) mbar_arrive(BAR(ex) + 8 * warp);
    }
    TS(9);
    cs_load(0);
#pragma unroll
    for (int f = 0; f < 10; f++) { kl[f] = fold(1, f, 0); vl[f] = fold(2, f, 0); }
#pragma unroll
    for (int f = 0; f < 10; f++) { ql[f] = fold(0, f, 0); qh[f] = fold(0, f, 1); }
    auto rs = [&](int i) { return __uint_as_float(lds32(s2u(&s_rstd[wg][16 * w + i]))); };
    const float kx0 = rs(2 * q + (sel0 ? 0 : 8)), kx1 = rs(2 * q + (sel1 ? 1 : 9)), ky0 = rs(2 * q + (sel0 ? 8 : 16)), ky1 = rs(2 * q + (sel1 ? 9 : 17));
    const float rx = SC * rs(8 + g), ry = SC * rs(16 + g), cx0 = rx * kx0, cx1 = rx * kx1, cy0 = ry * ky0, cy1 = ry * ky1;
    uint4 hv[5];
    const uint4* hp = &g_halo[bx - 1][wg][0][lane];
    auto prev = [&] {
        if (w > 0) {
            const uint32_t a = sb + Q_EOFF + wg * 8192 + (w - 1) * Q_ESLOT + mj * Q_EROW + mi * 16;
            mbar_wait(BAR(ex) + 8 * (warp - 1), 0);
            ldsm_x4(hv[0].x, hv[0].y, hv[0].z, hv[0].w, a);
            ldsm_x4(hv[1].x, hv[1].y, hv[1].z, hv[1].w, a + 64);
            ldsm_x4_t(hv[2].x, hv[2].y, hv[2].z, hv[2].w, a + 128);
            ldsm_x4_t(hv[3].x, hv[3].y, hv[3].z, hv[3].w, a + 192);
            ldsm_x2_t(hv[4].x, hv[4].y, a + 256);
            ldsm_x2(hv[4].z, hv[4].w, a + 288 - (lane >> 4) * 32);
        } else if (blk > 0) {
#pragma unroll
            for (int f = 0; f < 5; f++) hv[f] = ld_ll4(hp + 32 * f);
        } else {
#pragma unroll
            for (int f = 0; f < 5; f++) hv[f] = make_uint4(0, 0, 0, 0);
        }
    };
    if (A_HPOS == 0) prev();
    uint32_t vt[10][2];
#pragma unroll
    for (int f = 0; f < 10; f++) { vt[f][0] = movm_t(vl[f]); vt[f][1] = movm_t(vh[f]); }
    if (A_HPOS == 1) prev();
    TS(10);
    auto FA = [](int h) { return h == 0 ? 0 : h == 1 ? 3 : h == 2 ? 5 : 8; };
    auto FH = [](int h) { return h < 2 ? 2 : 7; };
    const uint32_t pm = (sel0 ? 0xFFFFu : 0u) | (sel1 ? 0xFFFF0000u : 0u);
    auto softmax = [&](float x0, float x1, float k0, float k1) {
        float mx = fmaxf(x0, x1);
        mx = fmaxf(mx, __shfl_xor_sync(~0u, mx, 1));
        mx = fmaxf(mx, __shfl_xor_sync(~0u, mx, 2));
        x0 = ex2(x0 - mx); x1 = ex2(x1 - mx);
        float sx = x0 + x1;
        sx += __shfl_xor_sync(~0u, sx, 1);
        sx += __shfl_xor_sync(~0u, sx, 2);
        const float ix = frcp(sx);
        return pack2(x0 * k0 * ix, x1 * k1 * ix);
    };
    uint32_t qm[4][2], py[4];
    float sl[4][2];
#pragma unroll
    for (int h = 0; h < 4; h++) {
        const int fa = FA(h), fb = fa + 1, fh = FH(h);
        const bool mine = (h & 1) ? (q >= 2) : (q < 2);
        qm[h][0] = mine ? ql[fh] : 0u; qm[h][1] = mine ? qh[fh] : 0u;
        float S1[4] = {0.f, 0.f, 0.f, 0.f}, S2[4] = {0.f, 0.f, 0.f, 0.f};
        mma16816(S1, ql[fa], qh[fa], ql[fb], qh[fb], kl[fa], kl[fb]); mma1688(S1, qm[h][0], qm[h][1], kl[fh]);
        mma16816(S2, ql[fa], qh[fa], ql[fb], qh[fb], kh[fa], kh[fb]); mma1688(S2, qm[h][0], qm[h][1], kh[fh]);
        sl[h][0] = S1[0]; sl[h][1] = S1[1];
        py[h] = softmax((sel0 ? S1[2] : S2[2]) * cy0, (sel1 ? S1[3] : S2[3]) * cy1, ky0, ky1);
    }
    TS(11);
    if (w == 0 && blk > 0) {
        int spin = 0;
        while (__any_sync(~0u, ((hv[0].x ^ ob) | (hv[1].x ^ ob) | (hv[2].x ^ ob) | (hv[3].x ^ ob) | (hv[4].x ^ ob)) & 1u) && ++spin < (1 << 18)) {
#pragma unroll
            for (int f = 0; f < 5; f++) hv[f] = ld_ll4(hp + 32 * f);
        }
#pragma unroll
        for (int f = 2; f < 4; f++) hv[f] = make_uint4(movm_t(hv[f].x), movm_t(hv[f].y), movm_t(hv[f].z), movm_t(hv[f].w));
        hv[4].x = movm_t(hv[4].x); hv[4].y = movm_t(hv[4].y);
    }
    const uint32_t kp[10] = {hv[0].x, hv[0].y, hv[4].z, hv[0].z, hv[0].w, hv[1].x, hv[1].y, hv[4].w, hv[1].z, hv[1].w};
    const uint32_t vp[10] = {hv[2].x, hv[2].y, hv[2].z, hv[2].w, hv[3].x, hv[3].y, hv[3].z, hv[3].w, hv[4].x, hv[4].y};
    TS(12);
    const uint4 ko[2] = {ldg_tab(16, tid & 127), ldg_tab(17, tid & 127)};
    const float bx0 = first && sel0 ? -INFINITY : 0.f, bx1 = first && sel1 ? -INFINITY : 0.f;
    float oacc[10][4];
#pragma unroll
    for (int h = 0; h < 4; h++) {
        const int fa = FA(h), fb = fa + 1, fh = FH(h);
        const bool mine = (h & 1) ? (q >= 2) : (q < 2);
        float S0[4] = {0.f, 0.f, 0.f, 0.f};
        mma16816(S0, ql[fa], qh[fa], ql[fb], qh[fb], kp[fa], kp[fb]); mma1688(S0, qm[h][0], qm[h][1], kp[fh]);
        const uint32_t px = softmax(fmaf(sel0 ? S0[0] : sl[h][0], cx0, bx0), fmaf(sel1 ? S0[1] : sl[h][1], cx1, bx1), kx0, kx1);
#pragma unroll
        for (int i = 0; i < 3; i++) {
            const int f = (i == 0) ? fa : (i == 1) ? fb : fh;
            float O[4] = {0.f, 0.f, 0.f, 0.f};
            mma16816(O, px & ~pm, py[h] & pm, 0u, py[h] & ~pm, vt[f][0], vt[f][1]);
            mma1688(O, px & pm, 0u, vp[f]);
            if (i < 2 || !(h & 1) || mine) { oacc[f][0] = O[0]; oacc[f][1] = O[1]; oacc[f][2] = O[2]; oacc[f][3] = O[3]; }
        }
    }
    TS(13);
    constexpr int ON = O_RING ? O_DEPTH + 2 : 7;
    uint4 of[ON][5];
    {
        uint4* dst = &g_of[hg][blk][warp][0][lane];
#pragma unroll
        for (int k = 0; k < 5; k++) {
            of[0][k] = make_uint4((pack2(oacc[2 * k][0], oacc[2 * k][1]) & ~1u) | ob, pack2(oacc[2 * k][2], oacc[2 * k][3]),
                                  pack2(oacc[2 * k + 1][0], oacc[2 * k + 1][1]), pack2(oacc[2 * k + 1][2], oacc[2 * k + 1][3]));
            st_ll4(dst + 32 * k, of[0][k].x, of[0][k].y, of[0][k].z, of[0][k].w);
        }
    }
    if (wg == 1 && lane == 0) mbar_arrive(BAR(att1));
    TS(14);
    const uint4* osrc = &g_of[0][blk][warp][0][lane];
    auto oload = [&](int j) {
        const uint4* p = osrc + osrc_of(j) * 20480;
#pragma unroll
        for (int k = 0; k < 5; k++) of[j % ON][k] = ld_ll4(p + 32 * k);
    };
    float aw[40];
    auto omma = [&](int j) {
        const uint64_t dm = mkdesc(sb + w_grp(j), 1280, 128, 0);
        wg_fence();
#pragma unroll
        for (int k = 0; k < 5; k++) wgmma_rs80(aw, of[j % ON][k], dm + k * 160, j + k > 0);
        wg_commit();
    };
    if (Q_WGATE && wg == 0) mbar_wait(BAR(att1), 0);
    mbar_wait(BAR(wfull), 0);
    omma(0);
    named_bar(1 + wg, 128);
    kernel_stage<2>(ko, sb + Q_KDUMP + 2 * wg * KG_RES, sb + F_EO + wg * 8192, w, lane);
    TS(8);
    {
        const uint32_t* pp = &g_of[osrc_of(1 + min(lane, 6))][blk][warp][4][31].x;
        uint32_t v, m;
        int spin = 0;
        do {
            asm volatile("ld.relaxed.gpu.global.u32 %0, [%1];" : "=r"(v) : "l"(pp) : "memory");
            m = __ballot_sync(~0u, (v & 1u) != ob);
        } while ((m & O_MASK) && ++spin < (1 << 18));
        TS(15);
        if (O_GATE) named_bar(O_GATE == 1 ? 1 + wg : 9, O_GATE == 1 ? 128 : 256);
#pragma unroll
        for (int j = 1; j <= O_DEPTH; j++) oload(j);
        TS(16);
    }
#pragma unroll
    for (int j = 1; j < 8; j++) {
        if (j == 3 || j == 7) mbar_wait(BAR(wfull) + 8 * ((j + 1) >> 2), 0);
        int spin = 0;
        while (true) {
            const uint4* f = of[j % ON];
            const uint32_t bad = ((f[0].x ^ ob) | (f[1].x ^ ob) | (f[2].x ^ ob) | (f[3].x ^ ob) | (f[4].x ^ ob)) & 1u;
            if (__all_sync(~0u, !bad) || ++spin >= (1 << 18)) break;
            oload(j);
        }
        if (j + O_DEPTH < 8) { if (O_RING || j == 2) wg_wait<1>(); oload(j + O_DEPTH); }
        if (j == 1) TS(17);
        if (j == 5) TS(18);
        omma(j);

    }
    wg_wait<2>();
    uint32_t res[20];
    mbar_wait(BAR(res), 0);
    const uint32_t ta = (8 * (mi >> 1) + mj) * 128 + (((2 * w + (mi & 1)) ^ mj) << 4);
    if (layer == 0) {
        const int tok = 16 * w + 8 * (mi & 1) + mj;
#pragma unroll
        for (int k = 0; k < 4; k++)
            ldsm_x4(res[4 * k], res[4 * k + 1], res[4 * k + 2], res[4 * k + 3], sb + W_RES + wg * 8192 + tok * 128 + (((2 * k + (mi >> 1)) ^ mj) << 4));
        ldsm_x4(res[16], res[17], res[18], res[19], sb + W_RES + 16384 + wg * 2048 + tok * 32 + (((mi >> 1) ^ (mj >> 2)) << 4));
    } else {
#pragma unroll
        for (int k = 0; k < 5; k++) ldsm_x4_t(res[4 * k], res[4 * k + 1], res[4 * k + 2], res[4 * k + 3], sb + W_RES + wg * 10240 + k * 2048 + ta);
    }
    mbar_wait(BAR(qdone), 0);
    wg_wait<0>();
    TS(19);
#pragma unroll
    for (int i = 0; i < 20; i++) {
        const uint32_t y = pack2(aw[2 * i], aw[2 * i + 1]);
        asm("add.rn.bf16x2 %0, %0, %1;" : "+r"(res[i]) : "r"(y));
    }
#pragma unroll
    for (int k = 0; k < 5; k++) stsm_x4_t(sb + W_OUT + wg * 10240 + k * 2048 + ta, res[4 * k], res[4 * k + 1], res[4 * k + 2], res[4 * k + 3]);
    fence_async_smem();
    named_bar(1 + wg, 128);
    if (w == 0 && elect_one()) {
        asm volatile("cp.async.bulk.tensor.2d.global.shared::cta.bulk_group [%0, {%2, %3}], [%1];"
                     ::"l"(TMAP(7)), "r"(sb + W_OUT + wg * 10240), "r"(1024 * wg + 64 * blk), "r"(hg * 80) : "memory");
        bulk_commit();
    }
    __syncwarp();
    conv_tables();
    TS(20);
    {
        float sm[4] = {0.f, 0.f, 0.f, 0.f}, d0[4] = {0.f, 0.f, 0.f, 0.f}, d1[4] = {0.f, 0.f, 0.f, 0.f};
#pragma unroll
        for (int k = 0; k < 5; k++) {
            mma16816(sm, res[4 * k], res[4 * k + 1], res[4 * k + 2], res[4 * k + 3], 0x3F803F80u, 0x3F803F80u);
            mma16816(d0, res[4 * k], res[4 * k + 1], res[4 * k + 2], res[4 * k + 3], res[4 * k], res[4 * k + 2]);
            mma16816(d1, res[4 * k], res[4 * k + 1], res[4 * k + 2], res[4 * k + 3], res[4 * k + 1], res[4 * k + 3]);
        }
        const bool diag = q == (g >> 1);
        if (diag || q == ((g >> 1) ^ 1)) {
            float* dst = g_sums[layer][diag] + 1024 * wg + 64 * blk + 16 * w + g;
            asm volatile("red.global.add.f32 [%0], %1;" ::"l"(dst), "f"(diag ? ((g & 1) ? d0[1] : d0[0]) : sm[0]) : "memory");
            asm volatile("red.global.add.f32 [%0], %1;" ::"l"(dst + 8), "f"(diag ? ((g & 1) ? d1[3] : d1[2]) : sm[2]) : "memory");
        }
    }
    TS(21);
    named_bar(1 + wg, 128);
    TS(22);
    TS_PHASE(2 * layer + 1);
    TS(0);
    indices();
    conv_wg<2>(5 * bx + 2 * (warp >> 2), layer, sb + F_EO + (warp >> 2) * 8192, sb + (warp >> 2) * Q_SB, sb + F_S23, s2u(&s_kg.kexp[2 * (warp >> 2)]),
               sb + 3 * Q_SB, BAR(st), warp, lane, fa1, ftw, [&] {
        if ((warp & 3) == 0 && elect_one()) { bulk_wait(); fence_async_global(); grid_arrive(g_bar[layer][hg]); }
        __syncwarp();
    }, [&] { mbar_wait(BAR(ardy), 0); }, [] {}, [] {} TS_PASS);
    conv_done();
    asm volatile("setmaxnreg.dec.sync.aligned.u32 168;");
    }
    named_bar(1 + (warp >> 2), 128);
    asm volatile("setmaxnreg.dec.sync.aligned.u32 %0;" ::"n"(504 - 2 * R_CONS));
    }
    indices();
    __syncthreads();
    if (FIN_DELAY) { const long long t0 = clock64(); while (clock64() - t0 < FIN_DELAY) {} }
    if (tid < 320) {
        const int p = warp & 1, cq = 4 * (warp >> 1) + (lane >> 3), tg = lane & 7;
        const uint4* src = (const uint4*)(g_x2T[1] + (size_t)(80 * hg + 4 * cq) * XP + 1024 * p + 64 * blk + 8 * tg);
        uint4 v[4];
#pragma unroll
        for (int i = 0; i < 4; i++) v[i] = make_uint4(0, 0, 0, 0);
        int spin = 0;
        while (true) {
            bool ok = true;
#pragma unroll
            for (int i = 0; i < 4; i++) if (v[i].x == 0u || v[i].z == 0u) v[i] = ld_ll4(src + i * (XP / 8));
#pragma unroll
            for (int i = 0; i < 4; i++) ok = ok && v[i].x != 0u && v[i].z != 0u;
            if (ok || ++spin >= (1 << 18)) break;
            if (FIN_SLEEP) __nanosleep(FIN_SLEEP);
        }
        TS(21);
#pragma unroll
        for (int i = 0; i < 8; i++) {
            const uint32_t sel = (i & 1) ? 0x7632 : 0x5410;
            asm volatile("st.shared.v2.u32 [%0], {%1, %2};" ::"r"(sb + (8 * (2 * i + p) + tg) * 160 + cq * 8),
                         "r"(__byte_perm(u4(v[0], i >> 1), u4(v[1], i >> 1), sel)), "r"(__byte_perm(u4(v[2], i >> 1), u4(v[3], i >> 1), sel)) : "memory");
        }
        fence_async_smem();
    }
    __syncthreads();
    if (warp == 0 && elect_one()) {
        asm volatile("cp.async.bulk.tensor.3d.global.shared::cta.bulk_group [%0, {%2, %3, 0}], [%1];" ::"l"(TMAP(9)), "r"(sb), "r"(80 * hg), "r"(8 * blk) : "memory");
        bulk_commit();
        asm volatile("cp.async.bulk.wait_group.read 0;" ::: "memory");
    }
    if (bx == 0 && tid == 0) g_epoch = EPOCH + 1;
    TS(22);
    TS_END;
}
typedef CUresult (*EncodeTiledFn)(CUtensorMap*, CUtensorMapDataType, cuuint32_t, void*, const cuuint64_t*, const cuuint64_t*, const cuuint32_t*,
                                  const cuuint32_t*, CUtensorMapInterleave, CUtensorMapSwizzle, CUtensorMapL2promotion, CUtensorMapFloatOOBfill);

static void make_map(EncodeTiledFn enc, CUtensorMap* m, const void* base, int rank, const cuuint64_t* dims, const cuuint64_t* strides,
                     const cuuint32_t* box, CUtensorMapSwizzle sw) {
    cuuint32_t es[4] = {1, 1, 1, 1};
    enc(m, CU_TENSOR_MAP_DATA_TYPE_BFLOAT16, rank, (void*)base, dims, strides, box, es, CU_TENSOR_MAP_INTERLEAVE_NONE, sw,
        sw == CU_TENSOR_MAP_SWIZZLE_128B ? CU_TENSOR_MAP_L2_PROMOTION_L2_128B : CU_TENSOR_MAP_L2_PROMOTION_NONE, CU_TENSOR_MAP_FLOAT_OOB_FILL_NONE);
}

template <typename... KArgs, typename... Args>
static void launch(void (*kern)(KArgs...), int grid, int block, int smem, int cluster, bool pdl, Args... args) {
    cudaLaunchConfig_t cfg = {};
    cfg.gridDim = dim3(grid); cfg.blockDim = dim3(block); cfg.dynamicSmemBytes = smem; cfg.stream = cudaStreamPerThread;
    cudaLaunchAttribute at[2];
    int n = 0;
    if (cluster > 1) { at[n].id = cudaLaunchAttributeClusterDimension; at[n].val.clusterDim.x = cluster; at[n].val.clusterDim.y = 1; at[n].val.clusterDim.z = 1; n++; }
    if (pdl) { at[n].id = cudaLaunchAttributeProgrammaticStreamSerialization; at[n].val.programmaticStreamSerializationAllowed = 1; n++; }
    cfg.attrs = at; cfg.numAttrs = n;
    cudaLaunchKernelEx(&cfg, kern, KArgs(args)...);
}

struct HostState {
    bool ready = false;
    const void* key[4] = {nullptr, nullptr, nullptr, nullptr};
    CUtensorMap mX[2], mRes[2], mW, mWr, mWo, mOut, mFin;
    bf16 *x1T, *x2T;
};

extern "C" void kernel_launch(void* const* d_in, const int* in_sizes, int n_in, void* d_out, int out_size) {
    const bf16* x = (const bf16*)d_in[0];
    const bf16* wqkv = (const bf16*)d_in[1];
    const bf16* wo = (const bf16*)d_in[2];
    const bf16* lar = (const bf16*)d_in[4];
    const bf16* aim = (const bf16*)d_in[5];
    const bf16* cre = (const bf16*)d_in[6];
    const bf16* cim = (const bf16*)d_in[7];
    const bf16* logdt = (const bf16*)d_in[8];
    const bf16* dskip = (const bf16*)d_in[9];
    static HostState hs;
    if (!hs.ready || hs.key[0] != wqkv || hs.key[1] != wo || hs.key[2] != x || hs.key[3] != d_out) {
        void* fn = nullptr;
        cudaDriverEntryPointQueryResult qr;
        cudaGetDriverEntryPoint("cuTensorMapEncodeTiled", &fn, cudaEnableDefault, &qr);
        EncodeTiledFn enc = (EncodeTiledFn)fn;
        cudaGetSymbolAddress((void**)&hs.x1T, g_x1T);
        cudaGetSymbolAddress((void**)&hs.x2T, g_x2T);
        {
            cuuint64_t d[3] = {DM, SEQ / 2, 2}, s[2] = {DM * 4, DM * 2};
            cuuint32_t b[3] = {64, 64, 2}, br[3] = {16, 64, 2};
            make_map(enc, &hs.mX[0], x, 3, d, s, b, CU_TENSOR_MAP_SWIZZLE_128B);
            make_map(enc, &hs.mRes[0], x, 3, d, s, br, CU_TENSOR_MAP_SWIZZLE_32B);
            cuuint64_t d2[3] = {SEQ / 2, DM, 2}, s2[2] = {XP * 2, SEQ};
            cuuint32_t b2[3] = {64, 80, 2};
            make_map(enc, &hs.mX[1], hs.x2T, 3, d2, s2, b, CU_TENSOR_MAP_SWIZZLE_128B);
            make_map(enc, &hs.mRes[1], hs.x2T, 3, d2, s2, b2, CU_TENSOR_MAP_SWIZZLE_128B);
            cuuint64_t d3[2] = {SEQ, DM};
            make_map(enc, &hs.mOut, hs.x1T, 2, d3, s2, b2, CU_TENSOR_MAP_SWIZZLE_128B);
        }
        { cuuint64_t d[2] = {3 * DM, DM}, s[1] = {3 * DM * 2}; cuuint32_t b[2] = {64, 32};
          make_map(enc, &hs.mW, wqkv, 2, d, s, b, CU_TENSOR_MAP_SWIZZLE_128B); }
        { cuuint64_t d[3] = {DM, DM, 3}, s[2] = {3 * DM * 2, DM * 2}; cuuint32_t b[3] = {16, 32, 3};
          make_map(enc, &hs.mWr, wqkv, 3, d, s, b, CU_TENSOR_MAP_SWIZZLE_32B); }
        { cuuint64_t d[4] = {8, 8, DM / 8, DM / 8}, s[3] = {DM * 2, 16, DM * 16}; cuuint32_t b[4] = {8, 8, 10, 5};
          make_map(enc, &hs.mWo, wo, 4, d, s, b, CU_TENSOR_MAP_SWIZZLE_NONE); }
        { cuuint64_t d[3] = {DM, SEQ / 16, 16}, s[2] = {DM * 32, DM * 2}; cuuint32_t b[3] = {80, 8, 16};
          make_map(enc, &hs.mFin, d_out, 3, d, s, b, CU_TENSOR_MAP_SWIZZLE_NONE); }
        cudaFuncSetAttribute(fused_kernel, cudaFuncAttributeMaxDynamicSharedMemorySize, Q_SMEM);
        hs.key[0] = wqkv; hs.key[1] = wo; hs.key[2] = x; hs.key[3] = d_out;
        hs.ready = true;
    }
    const SsmParams sp = {lar, aim, cre, cim, logdt, dskip};
    launch(fused_kernel, 128, 384, Q_SMEM, 2, false, sp, hs.mX[0], hs.mX[1], hs.mW, hs.mWr, hs.mRes[0], hs.mRes[1], hs.mOut, hs.mWo, hs.mFin);
}
```

```cpp
#include <cuda_runtime.h>
#include <cuda.h>
#include <cuda_bf16.h>
#include <cuda_fp16.h>
#include <stdint.h>

typedef __nv_bfloat16 bf16;

constexpr int SEQ = 2048;
constexpr int DM  = 640;
constexpr int XP  = SEQ + 64;
constexpr int NMODE = 192;

__device__ __forceinline__ uint32_t s2u(const void* p) { return (uint32_t)__cvta_generic_to_shared(p); }
__device__ __forceinline__ void mbar_init(uint32_t b, int c) { asm volatile("mbarrier.init.shared::cta.b64 [%0], %1;" ::"r"(b), "r"(c)); }
__device__ __forceinline__ void mbar_expect(uint32_t b, uint32_t bytes) { asm volatile("mbarrier.arrive.expect_tx.shared::cta.b64 _, [%0], %1;" ::"r"(b), "r"(bytes) : "memory"); }
__device__ __forceinline__ void mbar_arrive(uint32_t b) { asm volatile("mbarrier.arrive.shared::cta.b64 _, [%0];" ::"r"(b) : "memory"); }
__device__ __forceinline__ void mbar_arrive_cta(uint32_t b, uint32_t cta) {
    asm volatile("{\n.reg .b32 ra;\nmapa.shared::cluster.u32 ra, %0, %1;\nmbarrier.arrive.shared::cluster.b64 _, [ra];\n}" ::"r"(b), "r"(cta) : "memory");
}
__device__ __forceinline__ void mbar_wait(uint32_t b, uint32_t ph) {
#ifdef M_PLAIN
    asm volatile("{\n.reg .pred p;\nW: mbarrier.try_wait.parity.shared::cta.b64 p, [%0], %1;\n@!p bra W;\n}" ::"r"(b), "r"(ph) : "memory");
    return;
#endif
    asm volatile("{\n.reg .pred p;\n.reg .u32 n;\nmbarrier.try_wait.parity.shared::cta.b64 p, [%0], %1;\n@p bra D;\nmov.u32 n, 0;\n"
                 "W: mbarrier.try_wait.parity.shared::cta.b64 p, [%0], %1;\n@p bra D;\nadd.u32 n, n, 1;\nsetp.lt.u32 p, n, 4194304;\n@p bra W;\ntrap;\nD:\n}"
                 ::"r"(b), "r"(ph) : "memory");
}
__device__ __forceinline__ void fence_mbar_init() { asm volatile("fence.mbarrier_init.release.cluster;" ::: "memory"); }
__device__ __forceinline__ void cluster_sync() { asm volatile("barrier.cluster.arrive.aligned;\nbarrier.cluster.wait.aligned;" ::: "memory"); }
__device__ __forceinline__ void pdl_wait() { asm volatile("griddepcontrol.wait;" ::: "memory"); }
__device__ __forceinline__ void pdl_launch() { asm volatile("griddepcontrol.launch_dependents;" ::: "memory"); }
__device__ __forceinline__ void named_bar(int id, int n) { asm volatile("bar.sync %0, %1;" ::"r"(id), "r"(n) : "memory"); }
__device__ __forceinline__ void fence_async_smem() { asm volatile("fence.proxy.async.shared::cta;" ::: "memory"); }

__device__ __forceinline__ void tma2d(uint32_t dst, const CUtensorMap* m, int c0, int c1, uint32_t bar) {
    asm volatile("cp.async.bulk.tensor.2d.shared::cluster.global.mbarrier::complete_tx::bytes [%0], [%1, {%3, %4}], [%2];"
                 ::"r"(dst), "l"(m), "r"(bar), "r"(c0), "r"(c1) : "memory");
}
__device__ __forceinline__ void tma2d_mc(uint32_t dst, const CUtensorMap* m, int c0, int c1, uint32_t bar, uint16_t mask) {
    asm volatile("cp.async.bulk.tensor.2d.shared::cluster.global.mbarrier::complete_tx::bytes.multicast::cluster [%0], [%1, {%3, %4}], [%2], %5;"
                 ::"r"(dst), "l"(m), "r"(bar), "r"(c0), "r"(c1), "h"(mask) : "memory");
}
__device__ __forceinline__ void tma3d(uint32_t dst, const CUtensorMap* m, int c0, int c1, int c2, uint32_t bar) {
    asm volatile("cp.async.bulk.tensor.3d.shared::cluster.global.mbarrier::complete_tx::bytes [%0], [%1, {%3, %4, %5}], [%2];"
                 ::"r"(dst), "l"(m), "r"(bar), "r"(c0), "r"(c1), "r"(c2) : "memory");
}
__device__ __forceinline__ void tma3d_mc(uint32_t dst, const CUtensorMap* m, int c0, int c1, int c2, uint32_t bar, uint16_t mask) {
    asm volatile("cp.async.bulk.tensor.3d.shared::cluster.global.mbarrier::complete_tx::bytes.multicast::cluster [%0], [%1, {%3, %4, %5}], [%2], %6;"
                 ::"r"(dst), "l"(m), "r"(bar), "r"(c0), "r"(c1), "r"(c2), "h"(mask) : "memory");
}
__device__ __forceinline__ void bulk_g2s(uint32_t dst, const void* src, uint32_t bytes, uint32_t bar) {
    asm volatile("cp.async.bulk.shared::cluster.global.mbarrier::complete_tx::bytes [%0], [%1], %2, [%3];"
                 ::"r"(dst), "l"(src), "r"(bytes), "r"(bar) : "memory");
}
__device__ __forceinline__ void bulk_g2s_mc(uint32_t dst, const void* src, uint32_t bytes, uint32_t bar, uint16_t mask) {
    asm volatile("cp.async.bulk.shared::cluster.global.mbarrier::complete_tx::bytes.multicast::cluster [%0], [%1], %2, [%3], %4;"
                 ::"r"(dst), "l"(src), "r"(bytes), "r"(bar), "h"(mask) : "memory");
}
__device__ __forceinline__ void prefetch_l2(const void* p, uint32_t bytes) { asm volatile("cp.async.bulk.prefetch.L2.global [%0], %1;" ::"l"(p), "r"(bytes) : "memory"); }
__device__ __forceinline__ void prefetch_tmap(const CUtensorMap* m) { asm volatile("prefetch.tensormap [%0];" ::"l"(m) : "memory"); }

__device__ __forceinline__ void wg_fence() { asm volatile("wgmma.fence.sync.aligned;" ::: "memory"); }
__device__ __forceinline__ void wg_commit() { asm volatile("wgmma.commit_group.sync.aligned;" ::: "memory"); }
template <int N> __device__ __forceinline__ void wg_wait() { asm volatile("wgmma.wait_group.sync.aligned %0;" ::"n"(N) : "memory"); }
__device__ __forceinline__ uint64_t mkdesc(uint32_t addr, uint32_t lbo, uint32_t sbo, uint32_t mode) {
    return (uint64_t)((addr & 0x3FFFF) >> 4) | ((uint64_t)(lbo >> 4) << 16) | ((uint64_t)(sbo >> 4) << 32) | ((uint64_t)mode << 62);
}

__device__ __forceinline__ void mma16816(float (&c)[4], uint32_t a0, uint32_t a1, uint32_t a2, uint32_t a3, uint32_t b0, uint32_t b1) {
    asm("mma.sync.aligned.m16n8k16.row.col.f32.bf16.bf16.f32 {%0,%1,%2,%3},{%4,%5,%6,%7},{%8,%9},{%0,%1,%2,%3};"
                 : "+f"(c[0]), "+f"(c[1]), "+f"(c[2]), "+f"(c[3]) : "r"(a0), "r"(a1), "r"(a2), "r"(a3), "r"(b0), "r"(b1));
}
__device__ __forceinline__ void mma1688(float (&c)[4], uint32_t a0, uint32_t a1, uint32_t b0) {
    asm("mma.sync.aligned.m16n8k8.row.col.f32.bf16.bf16.f32 {%0,%1,%2,%3},{%4,%5},{%6},{%0,%1,%2,%3};"
                 : "+f"(c[0]), "+f"(c[1]), "+f"(c[2]), "+f"(c[3]) : "r"(a0), "r"(a1), "r"(b0));
}
__device__ __forceinline__ void ldsm_x4(uint32_t& r0, uint32_t& r1, uint32_t& r2, uint32_t& r3, uint32_t a) {
    asm volatile("ldmatrix.sync.aligned.m8n8.x4.shared.b16 {%0,%1,%2,%3}, [%4];" : "=r"(r0), "=r"(r1), "=r"(r2), "=r"(r3) : "r"(a) : "memory");
}
__device__ __forceinline__ void ldsm_x4_t(uint32_t& r0, uint32_t& r1, uint32_t& r2, uint32_t& r3, uint32_t a) {
    asm volatile("ldmatrix.sync.aligned.m8n8.x4.trans.shared.b16 {%0,%1,%2,%3}, [%4];" : "=r"(r0), "=r"(r1), "=r"(r2), "=r"(r3) : "r"(a) : "memory");
}
__device__ __forceinline__ void ldsm_x2(uint32_t& r0, uint32_t& r1, uint32_t a) {
    asm volatile("ldmatrix.sync.aligned.m8n8.x2.shared.b16 {%0,%1}, [%2];" : "=r"(r0), "=r"(r1) : "r"(a) : "memory");
}
__device__ __forceinline__ void ldsm_x2_t(uint32_t& r0, uint32_t& r1, uint32_t a) {
    asm volatile("ldmatrix.sync.aligned.m8n8.x2.trans.shared.b16 {%0,%1}, [%2];" : "=r"(r0), "=r"(r1) : "r"(a) : "memory");
}
__device__ __forceinline__ void stsm_x4(uint32_t a, uint32_t r0, uint32_t r1, uint32_t r2, uint32_t r3) {
    asm volatile("stmatrix.sync.aligned.m8n8.x4.shared.b16 [%0], {%1,%2,%3,%4};" ::"r"(a), "r"(r0), "r"(r1), "r"(r2), "r"(r3) : "memory");
}
__device__ __forceinline__ void stsm_x4_t(uint32_t a, uint32_t r0, uint32_t r1, uint32_t r2, uint32_t r3) {
    asm volatile("stmatrix.sync.aligned.m8n8.x4.trans.shared.b16 [%0], {%1,%2,%3,%4};" ::"r"(a), "r"(r0), "r"(r1), "r"(r2), "r"(r3) : "memory");
}
__device__ __forceinline__ void stsm_x2(uint32_t a, uint32_t r0, uint32_t r1) {
    asm volatile("stmatrix.sync.aligned.m8n8.x2.shared.b16 [%0], {%1,%2};" ::"r"(a), "r"(r0), "r"(r1) : "memory");
}
__device__ __forceinline__ uint32_t movm_t(uint32_t a) {
    uint32_t d;
    asm volatile("movmatrix.sync.aligned.m8n8.trans.b16 %0, %1;" : "=r"(d) : "r"(a));
    return d;
}
__device__ __forceinline__ uint32_t lds32(uint32_t a) { uint32_t v; asm volatile("ld.shared.u32 %0, [%1];" : "=r"(v) : "r"(a) : "memory"); return v; }
__device__ __forceinline__ uint32_t ldsv32(uint32_t a) { uint32_t v; asm volatile("ld.volatile.shared.u32 %0, [%1];" : "=r"(v) : "r"(a) : "memory"); return v; }
__device__ __forceinline__ void sts32(uint32_t a, uint32_t v) { asm volatile("st.shared.u32 [%0], %1;" ::"r"(a), "r"(v) : "memory"); }
__device__ __forceinline__ uint4 lds128(uint32_t a) { uint4 v; asm volatile("ld.shared.v4.u32 {%0,%1,%2,%3}, [%4];" : "=r"(v.x), "=r"(v.y), "=r"(v.z), "=r"(v.w) : "r"(a) : "memory"); return v; }
__device__ __forceinline__ void sts128(uint32_t a, uint4 v) { asm volatile("st.shared.v4.u32 [%0], {%1,%2,%3,%4};" ::"r"(a), "r"(v.x), "r"(v.y), "r"(v.z), "r"(v.w) : "memory"); }

__device__ __forceinline__ void stg128(void* p, uint4 v) { asm volatile("st.global.v4.u32 [%0], {%1,%2,%3,%4};" ::"l"(p), "r"(v.x), "r"(v.y), "r"(v.z), "r"(v.w) : "memory"); }

__device__ __forceinline__ uint4 ldg128(const void* p) { uint4 v; asm volatile("ld.global.v4.u32 {%0,%1,%2,%3}, [%4];" : "=r"(v.x), "=r"(v.y), "=r"(v.z), "=r"(v.w) : "l"(p) : "memory"); return v; }
__device__ __forceinline__ uint2 ldg64(const void* p) { uint2 v; asm volatile("ld.global.v2.u32 {%0,%1}, [%2];" : "=r"(v.x), "=r"(v.y) : "l"(p) : "memory"); return v; }
__device__ __forceinline__ uint32_t ldg32(const void* p) { uint32_t v; asm volatile("ld.global.u32 %0, [%1];" : "=r"(v) : "l"(p) : "memory"); return v; }

__device__ __forceinline__ uint32_t pack2(float lo, float hi) {
    uint32_t r;
    asm("cvt.rn.bf16x2.f32 %0, %1, %2;" : "=r"(r) : "f"(hi), "f"(lo));
    return r;
}
__device__ __forceinline__ float bf_lo(uint32_t v) { return __uint_as_float(v << 16); }
__device__ __forceinline__ float bf_hi(uint32_t v) { return __uint_as_float(v & 0xFFFF0000u); }
__device__ __forceinline__ float rbf(float x) { return __uint_as_float(pack2(0.f, x) & 0xFFFF0000u); }
__device__ __forceinline__ float ex2(float x) { float r; asm("ex2.approx.ftz.f32 %0, %1;" : "=f"(r) : "f"(x)); return r; }

__device__ __forceinline__ float2 ln_finish(float sum, float sumsq) {
    const float m = sum * (1.0f / DM);
    const float v = fmaxf(fmaf(sumsq, 1.0f / DM, -m * m), 0.f);
    float s, r;
    asm("sqrt.approx.ftz.f32 %0, %1;" : "=f"(s) : "f"(rbf(rbf(v) + 1e-5f)));
    asm("rcp.approx.ftz.f32 %0, %1;" : "=f"(r) : "f"(rbf(s)));
    return make_float2(m, r);
}
__device__ __forceinline__ uint32_t ln_finish_packed(float sum, float sumsq) {
    const float m = sum * (1.0f / DM);
    const float v = fmaxf(fmaf(sumsq, 1.0f / DM, -m * m), 0.f);
    float s;
    asm("sqrt.approx.ftz.f32 %0, %1;" : "=f"(s) : "f"(rbf(rbf(v) + 1e-5f)));
    return pack2(s, m);
}
__device__ __forceinline__ float frsq(float x) { float r; asm("rsqrt.approx.ftz.f32 %0, %1;" : "=f"(r) : "f"(x)); return r; }
__device__ __forceinline__ float frcp(float x) { float r; asm("rcp.approx.ftz.f32 %0, %1;" : "=f"(r) : "f"(x)); return r; }
__device__ __forceinline__ bool elect_one() {
    uint32_t p;
    asm volatile("{\n.reg .pred p;\nelect.sync _|p, 0xffffffff;\nselp.u32 %0, 1, 0, p;\n}" : "=r"(p));
    return p != 0;
}
__device__ __forceinline__ void cluster_arrive_relaxed() { asm volatile("barrier.cluster.arrive.relaxed.aligned;" ::: "memory"); }
__device__ __forceinline__ void cluster_wait() { asm volatile("barrier.cluster.wait.aligned;" ::: "memory"); }
__device__ __forceinline__ unsigned long long ld_ll(const unsigned long long* p) {
    unsigned long long v;
    asm volatile("ld.relaxed.gpu.global.b64 %0, [%1];" : "=l"(v) : "l"(p) : "memory");
    return v;
}
__device__ __forceinline__ void st_ll(unsigned long long* p, uint32_t payload, uint32_t tag) {
    const unsigned long long v = (unsigned long long)payload | ((unsigned long long)tag << 32);
    asm volatile("st.relaxed.gpu.global.b64 [%0], %1;" ::"l"(p), "l"(v) : "memory");
}
__device__ __forceinline__ uint4 ld_ll4(const uint4* p) {
    uint4 v;
    asm volatile("{\n.reg .b128 t;\n.reg .b64 a, b;\nld.relaxed.gpu.global.b128 t, [%4];\nmov.b128 {a, b}, t;\nmov.b64 {%0, %1}, a;\nmov.b64 {%2, %3}, b;\n}"
                 : "=r"(v.x), "=r"(v.y), "=r"(v.z), "=r"(v.w) : "l"(p) : "memory");
    return v;
}
__device__ __forceinline__ void st_ll4(uint4* p, uint32_t x, uint32_t y, uint32_t z, uint32_t w) {
    asm volatile("{\n.reg .b128 t;\n.reg .b64 a, b;\nmov.b64 a, {%1, %2};\nmov.b64 b, {%3, %4};\nmov.b128 t, {a, b};\nst.relaxed.gpu.global.b128 [%0], t;\n}"
                 ::"l"(p), "r"(x), "r"(y), "r"(z), "r"(w) : "memory");
}

__device__ __forceinline__ void bulk_s2g(void* dst, uint32_t src, uint32_t bytes) {
    asm volatile("cp.async.bulk.global.shared::cta.bulk_group [%0], [%1], %2;" ::"l"(dst), "r"(src), "r"(bytes) : "memory");
}
__device__ __forceinline__ void bulk_commit() { asm volatile("cp.async.bulk.commit_group;" ::: "memory"); }
__device__ __forceinline__ void bulk_wait() { asm volatile("cp.async.bulk.wait_group 0;" ::: "memory"); }
__device__ __forceinline__ void fence_async_global() { asm volatile("fence.proxy.async.global;" ::: "memory"); }
__device__ __forceinline__ void fence_release() { asm volatile("fence.release.gpu;" ::: "memory"); }
__device__ __forceinline__ void fence_acquire() { asm volatile("fence.acquire.gpu;" ::: "memory"); }
template<int TA, int TB>
__device__ __forceinline__ void wgmma_n192(float (&d)[96], uint64_t da, uint64_t db, int scale_d) {
  asm volatile("{\n.reg .pred p;\nsetp.ne.b32 p, %98, 0;\n"
    "wgmma.mma_async.sync.aligned.m64n192k16.f32.bf16.bf16 "
    "{%0, %1, %2, %3, %4, %5, %6, %7, %8, %9, %10, %11, %12, %13, %14, %15, %16, %17, %18, %19, %20, %21, %22, %23, %24, %25, %26, %27, %28, %29, %30, %31, %32, %33, %34, %35, %36, %37, %38, %39, %40, %41, %42, %43, %44, %45, %46, %47, %48, %49, %50, %51, %52, %53, %54, %55, %56, %57, %58, %59, %60, %61, %62, %63, %64, %65, %66, %67, %68, %69, %70, %71, %72, %73, %74, %75, %76, %77, %78, %79, %80, %81, %82, %83, %84, %85, %86, %87, %88, %89, %90, %91, %92, %93, %94, %95}, %96, %97, p, 1, 1, %99, %100;\n}\n"
    : "+f"(d[0]), "+f"(d[1]), "+f"(d[2]), "+f"(d[3]), "+f"(d[4]), "+f"(d[5]), "+f"(d[6]), "+f"(d[7]), "+f"(d[8]), "+f"(d[9]), "+f"(d[10]), "+f"(d[11]), "+f"(d[12]), "+f"(d[13]), "+f"(d[14]), "+f"(d[15]), "+f"(d[16]), "+f"(d[17]), "+f"(d[18]), "+f"(d[19]), "+f"(d[20]), "+f"(d[21]), "+f"(d[22]), "+f"(d[23]), "+f"(d[24]), "+f"(d[25]), "+f"(d[26]), "+f"(d[27]), "+f"(d[28]), "+f"(d[29]), "+f"(d[30]), "+f"(d[31]), "+f"(d[32]), "+f"(d[33]), "+f"(d[34]), "+f"(d[35]), "+f"(d[36]), "+f"(d[37]), "+f"(d[38]), "+f"(d[39]), "+f"(d[40]), "+f"(d[41]), "+f"(d[42]), "+f"(d[43]), "+f"(d[44]), "+f"(d[45]), "+f"(d[46]), "+f"(d[47]), "+f"(d[48]), "+f"(d[49]), "+f"(d[50]), "+f"(d[51]), "+f"(d[52]), "+f"(d[53]), "+f"(d[54]), "+f"(d[55]), "+f"(d[56]), "+f"(d[57]), "+f"(d[58]), "+f"(d[59]), "+f"(d[60]), "+f"(d[61]), "+f"(d[62]), "+f"(d[63]), "+f"(d[64]), "+f"(d[65]), "+f"(d[66]), "+f"(d[67]), "+f"(d[68]), "+f"(d[69]), "+f"(d[70]), "+f"(d[71]), "+f"(d[72]), "+f"(d[73]), "+f"(d[74]), "+f"(d[75]), "+f"(d[76]), "+f"(d[77]), "+f"(d[78]), "+f"(d[79]), "+f"(d[80]), "+f"(d[81]), "+f"(d[82]), "+f"(d[83]), "+f"(d[84]), "+f"(d[85]), "+f"(d[86]), "+f"(d[87]), "+f"(d[88]), "+f"(d[89]), "+f"(d[90]), "+f"(d[91]), "+f"(d[92]), "+f"(d[93]), "+f"(d[94]), "+f"(d[95])
    : "l"(da), "l"(db), "r"(scale_d), "n"(TA), "n"(TB));
}

template<int TA, int TB>
__device__ __forceinline__ void wgmma_n48(float (&d)[24], uint64_t da, uint64_t db, int scale_d) {
  asm volatile("{\n.reg .pred p;\nsetp.ne.b32 p, %26, 0;\n"
    "wgmma.mma_async.sync.aligned.m64n48k16.f32.bf16.bf16 "
    "{%0, %1, %2, %3, %4, %5, %6, %7, %8, %9, %10, %11, %12, %13, %14, %15, %16, %17, %18, %19, %20, %21, %22, %23}, %24, %25, p, 1, 1, %27, %28;\n}\n"
    : "+f"(d[0]), "+f"(d[1]), "+f"(d[2]), "+f"(d[3]), "+f"(d[4]), "+f"(d[5]), "+f"(d[6]), "+f"(d[7]), "+f"(d[8]), "+f"(d[9]), "+f"(d[10]), "+f"(d[11]), "+f"(d[12]), "+f"(d[13]), "+f"(d[14]), "+f"(d[15]), "+f"(d[16]), "+f"(d[17]), "+f"(d[18]), "+f"(d[19]), "+f"(d[20]), "+f"(d[21]), "+f"(d[22]), "+f"(d[23])
    : "l"(da), "l"(db), "r"(scale_d), "n"(TA), "n"(TB));
}

__device__ __forceinline__ void wgmma_rs80(float (&d)[40], const uint4& a, uint64_t db, int scale_d) {
  asm volatile("{\n.reg .pred p;\nsetp.ne.b32 p, %45, 0;\n"
    "wgmma.mma_async.sync.aligned.m64n80k16.f32.bf16.bf16 {%0,%1,%2,%3,%4,%5,%6,%7,%8,%9,%10,%11,%12,%13,%14,%15,%16,%17,%18,%19,%20,%21,%22,%23,%24,%25,%26,%27,%28,%29,%30,%31,%32,%33,%34,%35,%36,%37,%38,%39}, {%40,%41,%42,%43}, %44, p, 1, 1, 1;\n}\n"
    : "+f"(d[0]), "+f"(d[1]), "+f"(d[2]), "+f"(d[3]), "+f"(d[4]), "+f"(d[5]), "+f"(d[6]), "+f"(d[7]), "+f"(d[8]), "+f"(d[9]), "+f"(d[10]), "+f"(d[11]), "+f"(d[12]), "+f"(d[13]), "+f"(d[14]), "+f"(d[15]), "+f"(d[16]), "+f"(d[17]), "+f"(d[18]), "+f"(d[19]), "+f"(d[20]), "+f"(d[21]), "+f"(d[22]), "+f"(d[23]), "+f"(d[24]), "+f"(d[25]), "+f"(d[26]), "+f"(d[27]), "+f"(d[28]), "+f"(d[29]), "+f"(d[30]), "+f"(d[31]), "+f"(d[32]), "+f"(d[33]), "+f"(d[34]), "+f"(d[35]), "+f"(d[36]), "+f"(d[37]), "+f"(d[38]), "+f"(d[39])
    : "r"(a.x), "r"(a.y), "r"(a.z), "r"(a.w), "l"(db), "r"(scale_d));
}

__device__ const __align__(1024) uint32_t c_fft[11264] = {
0x2ddc2dba,0x2fe62eb5,0x2ed02eb5,0xafffaf6e,0x2e1f2dfe,0x2e3f2fbc,0x2f022ee9,0xad27af30,0x2e5e2e3f,0x1fd92b5e,0x2f302f1a,0x244ea875,0x2e992e7c,0xad96a993,0x2f5a2f46,0x2e992c32,
0xad00ad72,0xa17eac32,0xa17ea515,0xabb79cb6,0xac07ac87,0x2dfe29f1,0x1fd99648,0xafedae99,0xa9f1ab05,0x2fd42fbc,0x26a1244e,0xad96af91,0xa765a8d5,0x2aaa2e3f,0x29932875,0x2515a8d5,
0xae99adfe,0xb000aee9,0xaf6eafbc,0x2c872f30,0xaf80af1a,0xac32af02,0xae7caf02,0xaaaa217e,0xaff4afc9,0x2b5e9cb6,0xad27addc,0xaff4ae7c,0xafedb000,0x2ffc2eb5,0xab05ac5d,0xacd8af5a,
0x2c072d27,0x9fd92bb7,0xadfead00,0x2fed2e1f,0x25db2993,0xaf6eacb0,0xaf6eaed0,0x2c5d2f46,0xa5151648,0xaddcafdd,0xafffafd4,0xac321648,0xabb7a934,0x28d5a814,0xafa0afed,0xaff4af30,
0x2f302e3f,0x2fed2f1a,0x28142b5e,0x2934a875,0x30002fc9,0x26a12ddc,0xa5db1cb6,0x30002e7c,0x2f462fd4,0xaed0aa4e,0xacb0aa4e,0x29932e99,0x2d272e5e,0xae3faffc,0xaf02adfe,0xae1fa814,
0xa9f1acd8,0x26a1ab05,0x2fd42ffc,0xad96afed,0x2515a30e,0x2fff2e1f,0x2ddc2f1a,0x2c32a30e,0x2d272aaa,0x28752e7c,0x28752c32,0x2fa02f80,0x2f912e99,0xaee9a9f1,0xa8141648,0x9fd92c87,
0xafa0ae7c,0xafafaf46,0x2d002993,0xafa0ac32,0xaf91b000,0x244eac5d,0x2fbc2eb5,0xab05af5a,0xac87ae5e,0x30002dfe,0x2f6e2ffc,0x2e992814,0x1cb6a875,0x25152e1f,0x2c322e1f,0x2d722ff4,
0x27652c87,0xa9932a4e,0xaaaaadba,0xa5152c87,0xabb7a44e,0xafa0af30,0x28d59fd9,0xaff4ae5e,0xaf91ae1f,0x2814abb7,0x2ee92d00,0x1fd9ad27,0xaf5aafff,0x2fd42ed0,0x2fd42fe6,0x30002ddc,
0x2f462f6e,0x2c322fdd,0x2e7c2fdd,0xa993b000,0xab5e2934,0xafafacd8,0xad00244e,0x2f1a2dfe,0xaee9afaf,0x2f30a17e,0xadfeaff8,0xafbca30e,0x2c5da765,0xa9f12ddc,0x2d969cb6,0x2c5dacb0,
0x2bb7a993,0x2f1aa515,0x2f1a2765,0xaff4aaaa,0x2e5e2fd4,0xab052dba,0x29342f6e,0x2ee9a6a1,0xadba1fd9,0xa5dbafed,0xafddac07,0xaa4e2dfe,0xacb0aff8,0x2ddc2f02,0x9cb6ae3f,0xa765aff8,
0xaeb5af91,0xaa4eafed,0x9648ae5e,0xac5d2d4d,0x2ddca17e,0x2e7c2e3f,0x2fc92e3f,0x1cb6afa0,0x2bb72fe6,0xaff8a993,0xab5e2aaa,0x2bb72fc9,0xafbcaa4e,0x2f30a5db,0xadfeafdd,0xaee9adba,
0xacd828d5,0xaf91230e,0xaf30af02,0x2c072fa0,0xac5dafff,0x2dbaac32,0x2dbaa515,0xae99addc,0x2fc929f1,0xa9932eb5,0x2aaa2fdd,0x2fe629f1,0xa30e2dfe,0xa17eafed,0xaff8ac07,0xafaf1fd9,
0x2dfe2faf,0x28142ff8,0xae5e217e,0x2ffc230e,0xaf5aa515,0xac87af46,0xa6a1af80,0xaf5a2765,0x1cb6ae99,0x2e7c2dba,0x2fc92dba,0x2ddcac5d,0x2f1a2ee9,0xafafab05,0xad002934,0xab5e2e5e,
0x2dbaa814,0x2fdd9fd9,0x25db2f91,0x2a4eaee9,0x27652faf,0xaf4628d5,0xaf80ae1f,0xa5152faf,0xafa0addc,0x2e3fac32,0x2e3fa515,0xa17eafff,0x2dfea6a1,0xacd82dba,0x244e2f6e,0x29342fd4,
0xad27afc9,0xa30eafff,0x2faf2d72,0xad27ae7c,0x2ffc2a4e,0x28142fdd,0xae5e25db,0x2dfe2dba,0xac5d2c07,0xaa4eaf91,0x9648af30,0xaeb5acd8,0xa993aff4,0x2c322f1a,0x2e7c2f1a,0x2f462bb7,
0xae7c26a1,0xafff1648,0x2d72aa4e,0xafc926a1,0x230eaee9,0x2ff89fd9,0x217e2f91,0x2fafa814,0x2d4d2fa0,0xafed230e,0xae5eaf02,0xaf9128d5,0xb000aaaa,0x2fdda515,0x2fdd2765,0x2f6ea993,
0x9cb63000,0xacb02fd4,0xa7652fd4,0x2ddcaf5a,0x217eaffc,0x2ff4ac07,0x2875afbc,0xaff82934,0xa44e2ff4,0xadfea8d5,0xa9342fa0,0x2cd82bb7,0x25dbafe6,0x16482f46,0x29f1af80,0x25dbafc9,
0x2ff41cb6,0x2e1f2765,0x2e1f2cb0,0xa875addc,0xafbca5db,0x1fd9af5a,0xad4dad96,0xacd82fdd,0x2f5a2934,0xaeb52ee9,0x2c5d2e5e,0x3000ab05,0xaed0ab5e,0x2f80a30e,0xaaaaaf02,0xacb0ab5e,
0x25dbaffc,0x2d96afbc,0x2f5aac07,0xafdd2934,0xaaaa2fa0,0xafc92875,0xafe62875,0x29932d27,0x2d00aed0,0x28d52d72,0x2ff89cb6,0x2d00afe6,0xae5e2d96,0x2d4dafd4,0xaf91a6a1,0xafed29f1,
0xafbca17e,0xad4da875,0x1fd9aff4,0xacd82ff8,0x2e992aaa,0xaa4e2fe6,0xaa4e2fc9,0x2fd4a993,0xacb0ad96,0x2fffac87,0x2d72aeb5,0xa765ad96,0x28752f30,0xab5eac07,0xaf1a2cd8,0xae3f2f91,
0xa9342ff4,0xae5e2fa0,0xaee9a8d5,0x2b052bb7,0x2d96aed0,0x2eb59cb6,0x2c872d72,0x2d96afe6,0xaf802c5d,0x2765af6e,0xa515af6e,0xaf4625db,0x2ff8a44e,0xaff42d4d,0xa8752ffc,0xa17e2ee9,
0x2f5a244e,0x2c5d2934,0xaeb52dfe,0x3000acd8,0xacb0ad00,0x2d72aff8,0x2fffa8d5,0xa765ad00,0x217e2f80,0xaf022515,0xaf02a765,0xaf1a2f46,0x2b05afdd,0xa8142f5a,0x2c072d96,0x2d4d25db,
0x2b5eafe6,0x2f02af80,0x230e2f46,0x2b5eafc9,0xaf302d96,0xacd8a6a1,0x2c07afd4,0xaf9129f1,0x2fdda44e,0xad962ffc,0xaf5a2d4d,0xa5db2ee9,0xad72abb7,0x2e7ca17e,0x2fc9a17e,0x2fffad00,
0xaed0a5db,0xaaaaa9f1,0x2f809648,0xacb0a5db,0x28752e5e,0xaf1a2f91,0xab5ead4d,0xae3f2fed,0x2b05aff8,0x2c072875,0xa8142ff4,0x2d4d217e,0xaf6e2d72,0x2eb5afc9,0x2eb5ae7c,0x2dbaafff,
0xaf802f5a,0xafc92e99,0xafe62e99,0x2f46ad96,0x28d52b05,0xaf022fed,0x230e2cd8,0x2fa0affc,0x2fbcaf02,0xa9342d27,0x2ffcae1f,0x2c07ae3f,0xa6a1ac32,0x2a4e9cb6,0x9648ad72,0xa6a1a515,
0x28752aaa,0xa8d52cb0,0xa8d52ed0,0x2e3faf80,0x2fedaeb5,0x29349648,0x2f30aa4e,0x2814ac5d,0x1648ad4d,0x2e99acd8,0x2c87afbc,0xa9f11fd9,0xafe62d27,0x2fffafaf,0xaddc230e,0xaed02d27,
0x2fd4af30,0x2f6eae5e,0x2dbaa44e,0xa6a19fd9,0x1cb6ad27,0x2fe6aff4,0x2ed0aff4,0xad722b5e,0xafaf2cb0,0x2e1faf46,0xa8d5a993,0xafaf2ed0,0xac072f6e,0x2934ac87,0xaffc2e99,0xafbc3000,
0xa44eab5e,0x2b05ad00,0x2f91afaf,0xafbc2f1a,0xafd42d72,0x1648a765,0x1648acb0,0xafdd2fff,0xac322f5a,0xaaaa26a1,0xaf802c87,0xae7c2f5a,0x2d009fd9,0xae1f2cd8,0xad272fbc,0xabb72d4d,
0xaffc2f02,0xaee92e1f,0x244ead27,0xad4d2e3f,0xa9f12e7c,0xafdd2f80,0xaeb52aaa,0xa9f12c32,0x2d72a5db,0xafe63000,0xaed03000,0x9cb626a1,0x2fa0afbc,0xaf022f91,0x230e2b05,0x28d5a44e,
0x96482c07,0xac872d4d,0xae992b05,0x29f1a814,0x2ed0abb7,0xa9932b5e,0xaf462ff8,0x2cb0abb7,0x2f1aafff,0xa30e2765,0xa30e2cb0,0x2e1fad72,0x1fd9ac5d,0x244e9648,0x2e5eaa4e,0x2f30aeb5,
0x2ff8aed0,0x2e3faddc,0xaf022fff,0x2ff8afe6,0x2d4daf6e,0x2ee9ae99,0xa44e2c87,0x2ffcb000,0xa6a1a814,0x2f6eaf30,0x2dbaa934,0x2fd4afed,0xaf462d00,0x2fc9afa0,0x2fe6afa0,0x2f80afaf,
0x2515ac5d,0x2d72ad96,0x1cb629f1,0x2c32ac5d,0xad002814,0x2d27ad4d,0x2e1fab05,0x2bb7ac07,0xaffc2f1a,0x2cd8ad00,0x2fedafaf,0x2b05ab5e,0xadba2f80,0x2c87acb0,0x2c87aed0,0x2a4eaaaa,
0x2f802f6e,0x2fc92fdd,0x2fe62fdd,0xaf46b000,0x2fa02f91,0x2bb72e5e,0x2ff42fed,0xa8d5ad4d,0x2fbc2faf,0xa934217e,0x2ffc2ff8,0x2c07230e,0x2fd42fc9,0xaf5aad72,0x30002fff,0x2fd42e7c,
0x2bb72aaa,0x2f1a2cb0,0x2f1a2ed0,0xaff4af80,0x2cd82c5d,0x2f303000,0x2f912f5a,0xac07aeb5,0x2dba2d4d,0x25db2cd8,0x2fdd2fbc,0x2a4e9fd9,0x2e7c2e1f,0xad72a875,0x2fff2ff4,0x2fc92e1f,
0xa6a1a934,0x29f1a44e,0x2d962cd8,0xafd4adfe,0x1cb6a17e,0x2fe62e3f,0x2ed02e3f,0xad72afa0,0x28752515,0x2d272f80,0x2fa02f46,0x2875a765,0x2c072a4e,0xa93425db,0x2ffc2fdd,0x2fbc2dba,
0xae5eaf1a,0xa934ae3f,0x2b052875,0xaee9ab5e,0xac5dad72,0x2dba2765,0x2dba2cb0,0xae99afff,0xa765aa4e,0x2f802fd4,0x2f462e99,0x2515aa4e,0x230e9fd9,0x217e2cd8,0x2ff82fbc,0x2faf2d4d,
0xaffcafaf,0xaee9aff8,0x244ea17e,0xad4da30e,0xaf6eafe6,0x25dbaaaa,0x2c5d2993,0xaf6eafc9,0xad72ae99,0x2fe62dba,0x2ed02dba,0x1cb6ac5d,0xa8d5ac07,0x2bb72f30,0x2ff42f91,0x2fa02cd8,
0xadbaac07,0xafddad4d,0xa5dbab05,0xaa4e2814,0xafc9af02,0xaaaaaf1a,0x2993217e,0xafe6af02,0xafa0afff,0x2e3f2765,0x2e3f2cb0,0xa17ead72,0xad4daeb5,0x2e5e3000,0x2fed2f5a,0x2f912c5d,
0xa17e2765,0xad001cb6,0xabb7addc,0xa17e2cb0,0xad4daa4e,0xaee9afdd,0x244ea5db,0xaffcadba,0xafd4aee9,0x29f1a934,0x2d962b05,0xa6a1ae5e,0xaf46aff4,0x2fc92f1a,0x2fe62f1a,0x2f802bb7,
0x2cb02eb5,0x1cb62dba,0xaddcaf6e,0x27652eb5,0xa30e2814,0xaff8ad4d,0xa17eab05,0xafafac07,0xadfeab5e,0xa44eae3f,0x2cd82875,0xa934af1a,0xb000af80,0x2fdd2cb0,0x2fdd2ed0,0x2f6e2aaa,
0x2d723000,0x25152fd4,0x2c322fd4,0x1cb6af5a,0xae1f9fd9,0xae3faee9,0xaf02a814,0x2d272f91,0xacd8aff4,0x2ffc28d5,0xab05afa0,0xafedabb7,0x2e992515,0xad962aaa,0x2f5a2993,0x2e99a765,
0x2ff42ddc,0x2e1f2ed0,0x2e1f2fe6,0xa875afff,0xa8142c87,0xaffca9f1,0xadfe1648,0x2e5e2e99,0xaf5aaf30,0x2eb5a814,0xac5dafed,0xb000a934,0x2c32a8d5,0xa9932e3f,0x2f462875,0x2e7ca8d5,
0x2e991fd9,0x30002814,0x2f6e2ee9,0xac87af91,0x29932fa0,0xaed02875,0xacb02875,0x2f462d27,0xaff4ac32,0x2b5eaddc,0xad27afff,0xaff4a515,0x244ead96,0x1fd92fd4,0x2f3026a1,0x2e5ea9f1,
0x2814ad27,0x2dfeabb7,0x2ffc2d00,0xae5eae1f,0x2e992f80,0xaa4e2e7c,0xaa4e2c32,0x2fd42aaa,0xae7c1648,0x9cb6afdd,0xaddcafd4,0xafc91648,0xa875af91,0x2b5e2fbc,0x2f1a244e,0x2e3fab05,
0xab05aff4,0x244eafa0,0x2fbc28d5,0xaf91abb7,0x30002c32,0x26a12fff,0xa5db2ddc,0x30002515,0xaaaa2c5d,0xac32af6e,0xae7caf6e,0xaf8025db,0xad27afed,0x2e3f2dfe,0x2f021fd9,0x2e1fac07,
0xaf5aae5e,0xac5daf30,0x2eb59fd9,0xb000a44e,0x2e7ca30e,0x2ddc2e1f,0x1cb62f1a,0x2fc9a30e,0x217e2f46,0xaf02acb0,0xaf02aed0,0xaf1a2993,0xaf30ae99,0x2fbc29f1,0x2ee99648,0x2dfeac87,
0xafa0a515,0xafafa993,0x2d00aaaa,0xafa02765,0x2934ad96,0x2fed26a1,0x28142fd4,0x2f30a9f1,0x2c872fed,0xb0009fd9,0xaf6eadfe,0xae992c07,0xafffabb7,0x2fe6a17e,0x2ed0a17e,0x2ddcad00,
0xac322c87,0xaf462a4e,0x2993adba,0xae7c2c87,0xa875afed,0x2f1aab05,0x2b5e2ffc,0x2e3facd8,0x2f302e1f,0xaee92bb7,0xafbcad00,0xadfe2d27,0xaf6e9cb6,0x2eb5ac32,0x2eb5a515,0x2dbaad72,
0xaaaa2f5a,0xaed02e99,0xacb02e99,0x2f80ad96,0x2b5eaf30,0x2fafa44e,0x2d00ae5e,0xaf1a9fd9,0xac072f02,0xab05ad27,0xad4d2e1f,0x28142e3f,0x2c5daed0,0xa9f12fff,0x2d96addc,0x2c5dafe6,
0x28752f80,0xa8d52fe6,0xa8d52fc9,0x2e3faf46,0xa44eafd4,0x2f91adba,0x2b05af6e,0xafbc26a1,0x96482ffc,0xae99a44e,0xac872ee9,0x29f12d4d,0x2515aff8,0x1cb62f02,0x2d72ae3f,0x2c32aff8,
0x2eb52b05,0x2a4e2cd8,0x16482fed,0x2c5daffc,0xad72ad27,0x2cb0aff4,0x2765aff4,0xafff2b5e,0x2bb72e7c,0xaff82aaa,0xab5e2f80,0x2bb72c32,0xa814af6e,0x2b052c87,0x2d4dae99,0x2c07b000,
0x2feda8d5,0x2f30a30e,0x29342f02,0x2814afa0,0xafd49cb6,0x1648aed0,0x1648afe6,0xafdd2d72,0x2ed029f1,0xaf462eb5,0xa9932fdd,0x2cb029f1,0xad00ad4d,0x2e1f244e,0x2d27aee9,0x2bb7affc,
0x2d4daf02,0x2fbcae1f,0x2cd82d27,0x9fd9ae3f,0xaf5a2cb0,0xac87a993,0xa6a1af46,0xaf5a2ed0,0x2fffa5db,0xacb03000,0xa7653000,0x2d7226a1,0xaf1aa814,0x2fafa934,0x2d00af30,0x2b5eafed,
0x1648afbc,0x2c87affc,0x2e992934,0xa9f1ac07,0xac322faf,0xaf8028d5,0xaaaaae1f,0xae7c2faf,0x2f1aad72,0xa30e2ed0,0xa30e2fe6,0x2e1f1cb6,0xaffc26a1,0x2fedadba,0x2cd8af6e,0x2b05afd4,
0xad27ac32,0xa30ead72,0x2faf9cb6,0xad27a515,0x1fd92f6e,0xafbc2e99,0xacd8ac87,0xad4d3000,0x2c5dafbc,0x2a4e2b05,0x16482f91,0x2eb5a44e,0xaf802d00,0x2ed0afa0,0x2cb0afa0,0x2aaaafaf,
0xafe626a1,0xaddc1648,0x2fffaa4e,0xaed026a1,0x2d002c07,0xad272ffc,0xae1fa934,0xabb72fbc,0x1fd9afa0,0x2e5ea30e,0x244e2f02,0x2f30a8d5,0xadba2f46,0x2c87afe6,0x2c87afc9,0x2a4eaf80,
0xafff2d96,0xae7c2c5d,0xafc92c5d,0x2d72a9f1,0xa17e2dfe,0xaff42fbc,0xa8752ee9,0x2ff8af30,0x2fedad00,0xad4d2f1a,0x2f91ab5e,0x2e5eafaf,0x25dbae7c,0x16482993,0x29f1af46,0x25dbac32,
0xae3f2fff,0xaff82fc9,0xaff82e7c,0x2f02ad72,0x2c0725db,0xadfe2f5a,0x9fd92d96,0x2fedafdd,0x2f6eaf91,0xa6a12c07,0x2fd4acd8,0x2dbaaf30,0xa765ab5e,0x2aaaa30e,0x2993af02,0x2515ab5e,
0xa5db2dfe,0xad962ee9,0xaf5a2fbc,0x2fddaf30,0x2f46ab5e,0xa7652bb7,0x25152bb7,0x2f80aff8,0x2d00afc9,0x28d59cb6,0x2ff8addc,0x2d00ae7c,0xacd89648,0x2dfeac5d,0x2934aeb5,0x244eaa4e,
0x2c07217e,0x9fd92875,0xadfe2ff4,0x2fedaff8,0x2fddaf46,0x29f1a515,0x29f12765,0x2eb5af80,0x2515ad96,0x2ddcac87,0x2fffaeb5,0x2c32ad96,0xaf022b05,0x2fa0aee9,0x28d5ae5e,0x230ea934,
0x2f91ad00,0x2cd8ab5e,0xac072f1a,0x2f30afaf,0x2d96afc9,0x2eb5addc,0x2c879cb6,0x2d96ae7c,0xa993a6a1,0x2fc9af5a,0x2fe6af5a,0x2aaaac87,0xaff82e5e,0x2ff4affc,0x2875adfe,0x217ea814,
0x2f6eafed,0x2fd4af91,0xa6a12d4d,0x2dbaae5e,0x2515ad00,0x2fffaff8,0x2ddca8d5,0x2c32ad00,0xae1f2993,0x2fafafe6,0x2fafafc9,0x28d5aaaa,0xaf912fdd,0x2ee9af5a,0x2814ad96,0x1fd9a5db,
0x2b5eae7c,0x2f02af46,0x230e2993,0x2b5eac32,0xab059648,0x2e5eaeb5,0x2ee9ac5d,0x2934aa4e,0xafdd2e5e,0x2d96adfe,0x2f5aaffc,0x25dba814,0xaddc2faf,0x2cb0ad27,0x2765ad27,0x1cb6a30e,
0xa765a5db,0x2993a9f1,0x2aaa9648,0x2515a5db,0xaf022cd8,0x28d5a934,0x2fa0adfe,0x230ea44e,0xaf912ff8,0x2814a875,0x2ee9aff4,0x1fd9a17e,0xaa4e2ddc,0x26a1a765,0x26a1acb0,0x16489cb6,
0x2d722d96,0x25152c5d,0x2c322c5d,0x1cb6a9f1,0x2d272d4d,0xad00a814,0x2bb72c07,0x2e1f2b05,0x2cd82d00,0xaffcaf1a,0x2b052b5e,0x2fed2faf,0x2c872cb0,0xadbaaf80,0x2a4e2aaa,0x2c872ed0,
0x2e3f2ddc,0x2ff82ed0,0x2ff82fe6,0xaf02afff,0x2ee92e99,0x2d4d2f6e,0x2ffc3000,0xa44eac87,0x2f6e2f30,0xa6a12814,0x2fd42fed,0x2dba2934,0x2fc92fa0,0xaf46ad00,0x2f802faf,0x2fe62fa0,
0xac87ad4d,0x9648ac07,0x29f12814,0xae99ab05,0xa993ab5e,0x2ed02bb7,0x2cb02bb7,0xaf46aff8,0xa30ea765,0x2f1a2fff,0x2e1f2d72,0xa30eacb0,0x244e1648,0x1fd92c5d,0x2f302eb5,0x2e5e2a4e,
0xaee9ae1f,0xaffcaf02,0xad4dae3f,0x244e2d27,0xafddaf80,0xa9f1ae7c,0xa9f1ac32,0xaeb5aaaa,0xafe6b000,0x2d7225db,0x9cb6a6a1,0xaed0b000,0xaf02af91,0x2fa02fbc,0x28d5244e,0x230eab05,
0x2b052d00,0xa44e2b5e,0xafbcaf1a,0x2f912faf,0x16482765,0xafd4ad72,0xafddafff,0x16482cb0,0xaaaaa6a1,0xac32af5a,0xae7caf5a,0xaf80ac87,0xae1facd8,0x2d001fd9,0xabb7ad4d,0xad27afbc,
0x2f6e2e5e,0x2fd42f30,0xa6a11fd9,0x2dba244e,0x2fe62ff4,0x1cb62d27,0xad72ab5e,0x2ed02ff4,0x2e1f2f46,0xafafacb0,0xafafaed0,0xa8d52993,0x29342c87,0xac07af6e,0xafbcb000,0xaffcae99,
0xa8d5acb0,0x2875aaaa,0x2e3f2f80,0xa8d5aed0,0x29341648,0x2fed2eb5,0x28142c5d,0x2f302a4e,0x2e992cd8,0x16482d4d,0xa9f19fd9,0x2c872fbc,0x2fff2faf,0xafe6ad27,0xaed0ad27,0xaddca30e,
0xafc9ae99,0xaf80af5a,0x2f462d96,0xafe6ae99,0xaf02afed,0x28d5ab05,0x2fa02ffc,0x230eacd8,0xa934ad27,0x2fbc2f02,0x2c072e3f,0x2ffc2e1f,0x2a4e1cb6,0xa6a12c32,0xa6a12515,0x96482d72,
0xaaaa29f1,0xaed025db,0xacb025db,0x2f801648,0xaf1aaf91,0x2875ae5e,0xae3fafed,0xab5e2d4d,0x2c07a875,0x2b052ff8,0x2d4da17e,0xa814aff4,0x2eb52fc9,0xaf6ead72,0x2dba2fff,0x2eb52e7c,
0x2f022f80,0x2b5e2fe6,0x2b5e2fc9,0x230eaf46,0xacd826a1,0xaf30ad96,0xaf91a9f1,0x2c072fd4,0xad96affc,0x2fdd244e,0xa5dbaee9,0xaf5aad4d,0x2e7c217e,0xad722bb7,0x2fff2d00,0x2fc9217e,
0x2c5da934,0x2f5aa44e,0x30002cd8,0xaeb5adfe,0x2d722ff8,0xacb02d00,0xa7652d00,0x2fff28d5,0xaf02a515,0x217eaf80,0xaf1aaf46,0xaf022765,0xa814af5a,0x2b052fdd,0x2d4da5db,0x2c07ad96,
0xae5eafa0,0xa934aff4,0x2b05abb7,0xaee928d5,0x2eb51cb6,0x2d962ed0,0x2d962fe6,0x2c87ad72,0x27652f6e,0xaf80ac5d,0xaf46a5db,0xa5152f6e,0xaff4ad4d,0x2ff8244e,0xa17eaee9,0xa875affc,
0xad4d2875,0xafbc217e,0xacd8aff8,0x1fd92ff4,0xaa4eafe6,0x2e99aaaa,0x2fd42993,0xaa4eafc9,0x2fff2c87,0xacb02d96,0xa7652d96,0x2d722eb5,0xab5e2c07,0x2875af30,0xae3faf91,0xaf1aacd8,
0x2d962fbc,0x25db2ffc,0xafdda934,0x2f5a2c07,0xafc9a875,0xaaaaafa0,0x2993ad27,0xafe6a875,0x28d5ad72,0x2d002ed0,0x2d002fe6,0x2ff81cb6,0x2d4d2fd4,0xae5ead96,0xafeda9f1,0xaf9126a1,
0x2e1fa765,0x2ff49cb6,0xa8752ddc,0x2e1facb0,0x1fd92f5a,0xafbc25db,0xacd8afdd,0xad4d2d96,0xaeb5aee9,0x2f5aa934,0x30002b05,0x2c5dae5e,0x2f80230e,0xaed02b5e,0xacb02b5e,0xaaaa2f02,
0xacb0afd4,0x9cb6b000,0x2ddc2f5a,0xa765afd4,0x2ff42c07,0x217e2ffc,0xaff8a934,0x28752fbc,0xadfe28d5,0xa44eaff4,0x2cd8abb7,0xa934afa0,0x1648af46,0x25db2fe6,0x25db2fc9,0x29f12f80,
0xafff9648,0xae7ca6a1,0xafc9a6a1,0x2d722a4e,0x2ff81fd9,0x230e2ee9,0x2faf2814,0x217eaf91,0xafeda30e,0x2d4dafa0,0xaf91a8d5,0xae5e2f02,0x2fdd2515,0xb0002aaa,0x2f6e2993,0x2fdda765,
0xa30e2fff,0xad272fc9,0xad272e7c,0x2fafad72,0x2814afdd,0x2ffcaa4e,0x2dfeadba,0xae5ea5db,0xaa4e2f91,0xac5dac07,0xaeb52cd8,0x96482f30,0x2c32af1a,0xa9932ff4,0x2f46abb7,0x2e7caf1a,
0x2fdd1fd9,0x2dba2814,0x2a4e2ee9,0x25dbaf91,0xaf46a8d5,0x2765afaf,0xa515afaf,0xaf802e1f,0x2e3f2c32,0xafa02ddc,0xa17e2fff,0x2e3f2515,0xacd8adba,0x2dfe26a1,0x2934afd4,0x244eaf6e,
0x2814aff8,0x2dfeafaf,0x2ffca30e,0xae5ea17e,0xac872f46,0xaf5a2515,0xaf5aa765,0xa6a12f80,0x2e7cadba,0x1cb62e99,0x2ddc2c5d,0x2fc9adba,0xafaf2b05,0x2f1aaee9,0xab5eae5e,0xad00a934,
0xaf91a30e,0xacd8a8d5,0x2c07afa0,0xaf302f02,0x2dba2c32,0xac5d2fff,0xae992ddc,0x2dba2515,0xa993aeb5,0x2fc9a9f1,0x2fe6a9f1,0x2aaaafdd,0xa17e2fed,0xa30eadfe,0xafaf9fd9,0xaff82c07,
0xaa4e2fed,0xaeb52f91,0xac5dad4d,0x96482e5e,0x2e7cae3f,0x2ddc217e,0x1cb62fa0,0x2fc9ae3f,0xaff82993,0x2bb7afe6,0x2bb7afc9,0xab5eaaaa,0x2f3025db,0xafbc2a4e,0xaee92dba,0xadfe2fdd,
0x2f1a2515,0x2bb72993,0xaff42aaa,0x2f1aa765,0xab05adba,0x2e5eafd4,0x2ee926a1,0x2934af6e,0xa5db2fed,0xadba9fd9,0xaa4eadfe,0xafdd2c07,0x2ddcaf02,0xacb02ff8,0xa7652ff8,0x9cb62e3f,
0x2c32afdd,0x2f46af6e,0xa9933000,0x2e7cafdd,0xafaf2cd8,0xab5ea934,0x2f1aadfe,0xad00a44e,0x2f30217e,0xaee92faf,0xafbc230e,0xadfe2ff8,0xa9f1addc,0x2c5d2765,0x2c5d2cb0,0x2d961cb6,
0xa993aa4e,0x2765ac87,0xa515ac87,0xaaaa2dba,0xafa02f30,0xabb7244e,0xaff42e5e,0x28d51fd9,0x28142bb7,0xaf912e1f,0x1fd92d27,0x2ee9ad00,0x2fd4aed0,0xaf5a2fff,0x3000addc,0x2fd4afe6,
0xafaf2f46,0xafa02e7c,0xafa02c32,0x2d00a993,0x244e2c5d,0xaf913000,0xab052f5a,0x2fbcaeb5,0x3000adfe,0xac872e5e,0x2e99a814,0x2f6eaffc,0x2515ae1f,0x1cb62875,0x2d72aff4,0x2c32ae1f,
0x26a12b05,0xa9f12cd8,0xad962fed,0x2fd4affc,0x2fffae1f,0x2515230e,0x2c32230e,0x2ddcaf1a,0x2875ae7c,0x2d27aaaa,0x2fa0af80,0x2875ac32,0xaee929f1,0x2f91ae99,0x9fd9ac87,0xa8149648,
0x2fedaf1a,0x2f30ae3f,0x29342875,0x2814ab5e,0x26a1addc,0x3000afc9,0x3000ae7c,0xa5db9cb6,0xaed02a4e,0x2f46afd4,0x2993ae99,0xacb02a4e,0xae3f2ffc,0x2d27ae5e,0xae1f2814,0xaf022dfe,
0x9fd9abb7,0x2c07ad27,0x2fedae1f,0xadfe2d00,0xaf6e2cb0,0x25dba993,0x2c5daf46,0xaf6e2ed0,0xaddc2fdd,0xa5159648,0xac329648,0xafff2fd4,0x28d52814,0xabb72934,0xaff42f30,0xafa02fed,
0xb0002ee9,0xae992dfe,0x2c87af30,0xaf6e2fbc,0xac322f02,0xaf802f1a,0xaaaaa17e,0xae7c2f02,0x2b5e1cb6,0xaff42fc9,0xaff42e7c,0xad272ddc,0x2ffcaeb5,0xafed3000,0xacd82f5a,0xab052c5d,
0xa17e2c32,0xad002d72,0xabb71cb6,0xa17e2515,0x2dfea9f1,0xac072c87,0xafed2e99,0x1fd91648,0x2fd4afbc,0xa9f12b05,0xad962f91,0x26a1a44e,0x2aaaae3f,0xa76528d5,0x251528d5,0x2993a875,
0x2fe6aeb5,0x2ddcadba,0xafff2f6e,0x2ed0aeb5,0x2e3fafbc,0x2e1fadfe,0xad272f30,0x2f02aee9,0x1fd9ab5e,0x2e5eae3f,0x244e2875,0x2f30af1a,0xad962993,0x2e99ae7c,0x2e99ac32,0x2f5aaf46,
0x299329f1,0xa76525db,0x251525db,0x2aaa1648,0x28d52934,0xaf02acd8,0x230e244e,0x2fa02dfe,0x28142875,0xaf91aff8,0x1fd9217e,0x2ee92ff4,0x26a12765,0xaa4eaddc,0x16481cb6,0x26a12cb0,
0x2f022f46,0x2b5e2e7c,0x2b5e2c32,0x230ea993,0x2e5e2eb5,0xab051648,0x29342a4e,0x2ee92c5d,0x2d962dfe,0xafddae5e,0x25db2814,0x2f5a2ffc,0x2cb02d27,0xaddcafaf,0x1cb6230e,0x27652d27,
0x2fd42f91,0x2f6e2fed,0x2dba2e5e,0xa6a1ad4d,0x2fff2ff8,0x25152d00,0x2c322d00,0x2ddc28d5,0x2faf2fe6,0xae1fa993,0x28d52aaa,0x2faf2fc9,0x2ee92f5a,0xaf91afdd,0x1fd925db,0x28142d96,
0x2cd82b5e,0x2f912d00,0x2f302faf,0xac07af1a,0x2eb52ddc,0x2d962fc9,0x2d962e7c,0x2c871cb6,0x2fc92f5a,0xa99326a1,0x2aaa2c87,0x2fe62f5a,0x2ff42ffc,0xaff8ae5e,0x217e2814,0x28752dfe,
0x9fd9a875,0x2c07a17e,0x2fed2ff8,0xadfeaff4,0x29f12515,0x2fdd2f46,0x2eb52f80,0x29f1a765,0x2ddc2c87,0x25152d96,0x2c322d96,0x2fff2eb5,0x2fa02ee9,0xaf02ab05,0x230e2934,0x28d52e5e,
0xad96aee9,0xa5dbadfe,0x2fdd2f30,0xaf5aafbc,0xa765abb7,0x2f462b5e,0x2f802ff8,0x2515abb7,0x28d51cb6,0x2d002fc9,0x2d002e7c,0x2ff82ddc,0x2dfe2c5d,0xacd81648,0x244e2a4e,0x29342eb5,
0xaff8afc9,0xae3fafff,0x2f022d72,0xaff8ae7c,0xadfeaf5a,0x2c07a5db,0x2fed2fdd,0x9fd9ad96,0xa6a1ac07,0x2f6e2f91,0x2dba2f30,0x2fd42cd8,0x2aaa230e,0xa7652b5e,0x25152b5e,0x29932f02,
0xae7cac5d,0xafffad96,0x2d7229f1,0xafc9ac5d,0xaff4afbc,0xa17eadfe,0x2ff82f30,0xa875aee9,0xad4daf1a,0x2fed2d00,0x2e5e2faf,0x2f912b5e,0x1648a993,0x25db2e7c,0x25db2c32,0x29f12f46,
0xaddc9648,0xafe6a6a1,0xaed0a6a1,0x2fff2a4e,0xad27affc,0x2d00ac07,0xabb7afbc,0xae1f2934,0x2e5e230e,0x1fd92fa0,0x2f3028d5,0x244eaf02,0x2c872fe6,0xadbaaf46,0x2a4e2f80,0x2c872fc9,
0xa30e2d72,0xad272c32,0xad272515,0x2faf1cb6,0xafbcae99,0x1fd9af6e,0xad4db000,0xacd82c87,0x2a4eab05,0x2c5d2fbc,0x2eb5244e,0x1648af91,0x2ed02fa0,0xaf80ad00,0x2aaa2faf,0x2cb02fa0,
0x2c872ffc,0x16482fbc,0xa9f12c07,0x2e99a934,0xaf80a8d5,0xac32afaf,0xae7cafaf,0xaaaa2e1f,0xa30eaed0,0x2f1a2d72,0x2e1f9cb6,0xa30eafe6,0x2fed2dba,0xaffca6a1,0x2b052fd4,0x2cd82f6e,
0x2fbc2e1f,0x2d4d2f02,0x9fd92e3f,0x2cd8ad27,0xac872993,0xaf5aacb0,0xaf5aaed0,0xa6a12f46,0xacb0b000,0x2fff25db,0x2d72a6a1,0xa765b000,0x2faf2934,0xaf1a2814,0x2b5e2fed,0x2d002f30,
0x2f30230e,0x2fed28d5,0x28142fa0,0x2934af02,0x16482ed0,0xafd41cb6,0xafddad72,0x16482fe6,0xaf46aeb5,0x2ed0a9f1,0x2cb0a9f1,0xa993afdd,0x2e1fa44e,0xad002d4d,0x2bb72ffc,0x2d272ee9,
0x2a4eacd8,0x2eb5ab05,0x2c5d2ffc,0x1648afed,0x2cb02ff4,0xad722d27,0xafffab5e,0x27652ff4,0xaff8aaaa,0x2bb7ae7c,0x2bb7ac32,0xab5eaf80,0x2b05ac87,0xa8142f6e,0x2c073000,0x2d4d2e99,
0xa8d5afe6,0x2875af80,0x2e3f2f46,0xa8d5afc9,0x2f912dba,0xa44e2fd4,0xafbca6a1,0x2b052f6e,0xae99244e,0x9648affc,0x29f1ad4d,0xac87aee9,0x1cb6af02,0x25152ff8,0x2c322ff8,0x2d722e3f,
0xaed0ae99,0xaaaaaf5a,0x2f802d96,0xacb0ae99,0x2faf244e,0x2b5e2f30,0xaf1a1fd9,0x2d002e5e,0xab052d27,0xac07af02,0x2814ae3f,0xad4dae1f,0xa9f1afff,0x2c5d2ed0,0x2c5d2fe6,0x2d962ddc,
0xaf46aa4e,0xac32ac87,0xae7cac87,0x29932dba,0x2f1a2b05,0xa8752fed,0x2e3f2cd8,0x2b5eaffc,0xaee9abb7,0x2f30ae1f,0xadfead27,0xafbc2d00,0x2eb52c32,0xaf6e1cb6,0x2dba2d72,0x2eb52515,
0xafaf2993,0xafa02515,0xafa0a765,0x2d002aaa,0x2feda6a1,0x29342d96,0x2f3029f1,0x2814afd4,0xb0001fd9,0x2c87afed,0xae99ac07,0xaf6e2dfe,0x2fe6217e,0xafff2bb7,0x2ddc2d00,0x2ed0217e,
0xac5d2f30,0xaf5a2e5e,0xb000244e,0x2eb51fd9,0x2ddcae1f,0x2e7c230e,0x2fc9230e,0x1cb6af1a,0xaf022cb0,0x217eaf46,0xaf1aa993,0xaf022ed0,0x2fbca9f1,0xaf302e99,0x2dfe2c87,0x2ee91648,
0x244e2fa0,0xab052ff4,0xaf912bb7,0x2fbca8d5,0x26a1afff,0x3000ac32,0x3000a515,0xa5dbaddc,0xac322f6e,0xaaaaac5d,0xaf80a5db,0xae7c2f6e,0x2e3fadfe,0xad272fed,0x2e1f2c07,0x2f029fd9,
0x2dfe2bb7,0x28142d27,0xae5e2e1f,0x2ffcad00,0xaa4eae7c,0x2e99af80,0x2fd4aaaa,0xaa4eac32,0x9cb62fdd,0xae7c9648,0xafc99648,0xaddc2fd4,0x2b5eafbc,0xa8752f91,0x2e3f2b05,0x2f1aa44e,
0x3000a814,0x2e999fd9,0xac872f91,0x2f6eaee9,0xaed0a875,0x2993afa0,0x2f46ad27,0xacb0a875,0x2b5e2ddc,0xaff42c32,0xaff42515,0xad272fff,0x1fd9afd4,0x244e2d96,0x2e5e29f1,0x2f30a6a1,
0x2e1faed0,0x2ff4addc,0xa8752fff,0x2e1fafe6,0xaffc29f1,0xa814ac87,0x2e5eae99,0xadfe9648,0x2eb52814,0xaf5a2f30,0xb0002934,0xac5d2fed,0xa993ae3f,0x2c3228d5,0x2e7c28d5,0x2f46a875,
0x2515afd4,0x2d72b000,0x1cb62f5a,0x2c32afd4,0xae3f2ee9,0xae1f1fd9,0x2d27af91,0xaf022814,0x2ffca8d5,0xacd82ff4,0xafed2bb7,0xab052fa0,0xad96aaaa,0x2e99a515,0x2e992765,0x2f5aa993,
0x1cb6adba,0x2cb0aeb5,0x2765aeb5,0xaddc2f6e,0xaff82d4d,0xa30ea814,0xafaf2c07,0xa17e2b05,0xa44e2e3f,0xadfe2b5e,0xa9342f1a,0x2cd8a875,0x2fddacb0,0xb0002f80,0x2f6eaaaa,0x2fddaed0,
0xad009cb6,0xa17ea765,0xa17eacb0,0xabb72ddc,0xaee92fdd,0xad4d2a4e,0xaffc2dba,0x244e25db,0x29f12934,0xafd42ee9,0xa6a12e5e,0x2d96ab05,0x2fc9af1a,0xaf462ff4,0x2f80abb7,0x2fe6af1a,
0xafdd2d4d,0xadba2c07,0xaa4ea814,0xa5db2b05,0xaaaa2f1a,0xafc92f02,0xafe62f02,0x2993a17e,0x2e3fa765,0xafa02fff,0xa17e2d72,0x2e3facb0,0x2e5eb000,0xad4d2eb5,0x2f91ac5d,0x2fedaf5a,
0xaee92ff8,0xaffc2faf,0xad4d230e,0x244e217e,0x25db2aaa,0xaf6e2fe6,0xaf6e2fc9,0x2c5da993,0x2fe6adba,0xad722e99,0x1cb62c5d,0x2ed0adba,0x2bb7af30,0xa8d52c07,0x2fa0acd8,0x2ff4af91,
0xa9342e3f,0xae5e2f1a,0xaee92b5e,0x2b05a875,0x2dbaa765,0xac5d2d72,0xae992fff,0x2dbaacb0,0x2f80afd4,0xa7652a4e,0x25152a4e,0x2f46ae99,0x217eacd8,0x230e1fd9,0x2fafad4d,0x2ff8afbc,
0x29f1244e,0xa6a12934,0xafd42dfe,0x2d96acd8,0x2fe6ae3f,0x1cb6217e,0xad722fa0,0x2ed0ae3f,0x2d27af80,0x2875a515,0x28752765,0x2fa0af46,0xa934a5db,0x2c07aa4e,0x2fbcadba,0x2ffcafdd,
0x2f1aacb0,0x2bb7aaaa,0xaff42f80,0x2f1aaed0,0x2f30b000,0x2cd8ac5d,0xac072eb5,0x2f91af5a,0x25dbacd8,0x2dbaad4d,0x2a4e1fd9,0x2fddafbc,0xad722875,0x2e7cae1f,0x2fc9ae1f,0x2fffaff4,
0x2fc9afdd,0x2f80af6e,0xaf463000,0x2fe6afdd,0x2bb7ae5e,0x2fa0af91,0xa8d52d4d,0x2ff4afed,0xa934a17e,0x2fbcafaf,0x2c07a30e,0x2ffcaff8,0xaf5a2d72,0x2fd4afc9,0x2fd4ae7c,0x3000afff,
0x9d4d9e16,0xada6ae7d,0x9b769c84,0xabf0accf,0x985299e4,0xa897aa43,0x90b6957f,0xa102a5d8,0x13db0a48,0x242c1aad,0x191b1712,0x296d2783,0x1c201aad,0x2c632b1a,0x1db21ce9,0x2e112d3a,
0xa3f4a491,0xae51af42,0xa199a2c6,0xac70ad60,0x9e7ba06b,0xa922ab00,0x97129c20,0xa199a688,0x19e410b6,0x24aa1b76,0x1fa81d4d,0x2a112833,0x222f2102,0x2ce82bf0,0x2445235d,0x2ec92dd8,
0xa6a1a79c,0xaefcb004,0xa4aaa5a5,0xace8adf2,0xa166a35d,0xa9acabbe,0x99e49edf,0xa22fa738,0x1ce913db,0x25281c20,0x2262206b,0x2ab528a4,0x2528242c,0x2d6d2c63,0x271f2623,0x2f822e77,
0xa8a4a954,0xafa8b067,0xa688a7e8,0xad60ae84,0xa38fa528,0xaa37ac3d,0x9c20a0d0,0xa2c6a7e8,0x1edf157f,0x25a51c84,0x2478222f,0x2b592915,0x273825d8,0x2df22ccf,0x28fc284c,0x301d2f16,
0xa9f8aadb,0xb02ab0ca,0xa833a915,0xadd8af16,0xa4dca6a1,0xaac1ac9c,0x9d4da22f,0xa35da84c,0x206b1712,0x26231ce9,0x25bf23f4,0x2bfd2987,0x28a42783,0x2e772d3a,0x2a692987,0x307a2fb5,
0xab4cac31,0xb081b12e,0xa922aa37,0xae51afa8,0xa5f1a80d,0xab4cacfb,0x9e7ba38f,0xa3f4a8a4,0x21661852,0x26a11d4d,0x270524dc,0x2c5029f8,0x29ac2897,0x2efc2da6,0x2bd72ac1,0x30d7302a,
0xac50acf5,0xb0d7b192,0xaa11ab59,0xaec9b01d,0xa705a8ca,0xabd7ad5a,0x9fa8a478,0xa445a8fc,0x2262191b,0x271f1db2,0x282625bf,0x2ca22a69,0x2ab5296d,0x2f822e11,0x2ca22bfd,0x3135307a,
0xacfbadb9,0xb12eb1f7,0xab00ac3d,0xaf42b067,0xa80da987,0xac31adb9,0xa06ba528,0xa491a954,0x235d19e4,0x279c1e16,0x28ca26a1,0x2cf52adb,0x2bbe2a43,0x30042e7d,0x2d5a2c9c,0x319230ca,
0xb185b25c,0xb426b4cc,0xafbbb0b1,0xb1c6b306,0xac76ae18,0xaea3b08a,0xa4dca9ac,0xa738ac37,0x280d1e7b,0x2a0520d0,0x2d472b4c,0x2fdb2d6d,0x30472ee9,0x32663128,0x31f0311b,0x347933a8,
0xb1ddb2c1,0xb453b501,0xb01ab0fb,0xb204b352,0xacbcae77,0xaee9b0ba,0xa528aa05,0xa783ac63,0x284c1edf,0x2a432102,0x2d992bbe,0x30172da6,0x308a2f55,0x32aa315f,0x324f316b,0x34aa33fc,
0xb235b327,0xb481b537,0xb057b145,0xb242b39e,0xad01aed6,0xaf2fb0eb,0xa573aa5d,0xa7cfac90,0x288b1f44,0x2a822134,0x2deb2c18,0x30412ddf,0x30ce2fc2,0x32ef3196,0x32ae31bc,0x34db3428,
0xb28db38e,0xb4afb56d,0xb094b18f,0xb280b3eb,0xad47af36,0xaf75b11b,0xa5bfaab5,0xa80dacbc,0x28ca1fa8,0x2ac12166,0x2e3e2c50,0x306a2e18,0x31113017,0x333531cd,0x330d320e,0x350d3452,
0xb2e5b3f5,0xb4ddb5a3,0xb0d1b1da,0xb2beb41c,0xad8caf95,0xafbbb14b,0xa60aab0d,0xa833ace8,0x29092006,0x2b002199,0x2e902c89,0x30942e51,0x3155304d,0x337a3204,0x336d325f,0x3540347c,
0xb33eb42e,0xb50cb5da,0xb10eb224,0xb2fcb443,0xadd2aff5,0xb001b17c,0xa655ab65,0xa859ad14,0x29482039,0x2b4021cb,0x2ee32cc2,0x30be2e8a,0x31993084,0x33c0323b,0x33cd32b1,0x357234a6,
0xb398b463,0xb53ab612,0xb14bb26f,0xb33bb469,0xae18b02a,0xb024b1ac,0xa6a1abbe,0xa87ead40,0x2987206b,0x2b7f21fd,0x2f362cfb,0x30e72ec3,0x31dd30ba,0x34033273,0x34173303,0x35a534d1,
0xb3f2b497,0xb569b64a,0xb189b2bb,0xb37ab490,0xae5eb05a,0xb047b1dd,0xa6ecac0b,0xa8a4ad6d,0x29c6209d,0x2bbe222f,0x2f882d34,0x31112efc,0x322130f1,0x342632aa,0x34483356,0x35d934fc,
0xb599b682,0xb722b82e,0xb3b9b4b7,0xb4ddb5f9,0xb06ab20e,0xb185b398,0xa8caad99,0xa9f8aefc,0x2bfd2262,0x2cfb23f4,0x313b2f36,0x328d3081,0x344932e2,0x35693453,0x360d3527,0x37bd368b,
0xb5c9b6bb,0xb755b84d,0xb3f8b4df,0xb4feb622,0xb08db23e,0xb1a9b3ca,0xa8f0adc5,0xaa1eaf29,0x2c1e2294,0x2d1b2413,0x31652f6f,0x32b7309d,0x346d331a,0x358e3470,0x36413553,0x37f536ba,
0xb5f9b6f5,0xb789b86d,0xb41cb506,0xb51fb64c,0xb0b1b26f,0xb1cdb3fc,0xa915adf2,0xaa43af55,0x2c3d22c6,0x2d3a242c,0x318f2fa8,0x32e230ba,0x34903352,0x35b3348d,0x3676357e,0x381736e8,
0xb629b72f,0xb7bdb88d,0xb43cb52e,0xb540b676,0xb0d4b2a1,0xb1f0b417,0xa93bae1e,0xaa69af82,0x2c5d22f9,0x2d5a2445,0x31b92fe2,0x330d30d7,0x34b4338b,0x35d934aa,0x36ab35ab,0x38343717,
0xb65ab76a,0xb7f1b8ad,0xb45cb556,0xb561b6a0,0xb0f7b2d2,0xb214b430,0xa961ae4b,0xaa8fafaf,0x2c7d232b,0x2d79245f,0x31e3300e,0x333830f4,0x34d833c3,0x35fe34c7,0x36e035d7,0x38513746,
0xb68bb7a5,0xb813b8ce,0xb47cb57e,0xb582b6ca,0xb11bb303,0xb238b449,0xa987ae77,0xaab5afdb,0x2c9c235d,0x2d992478,0x320e302a,0x33633111,0x34fc33fc,0x362434e4,0x37173604,0x386f3775,
0xb6bdb7e2,0xb82eb8f0,0xb49cb5a7,0xb5a3b6f5,0xb13eb335,0xb25cb463,0xa9acaea3,0xaadbb004,0x2cbc238f,0x2db92491,0x32383047,0x338e312e,0x3520341a,0x364a3501,0x374d3631,0x388d37a5,
0xb6efb80f,0xb849b911,0xb4bdb5d0,0xb5c5b720,0xb162b366,0xb280b47c,0xa9d2aed0,0xab00b01a,0x2cdb23c2,0x2dd824aa,0x32623064,0x33b9314b,0x35453437,0x3670351f,0x3785365e,0x38ab37d6,
0xb865b934,0xb94dba5c,0xb5e7b74c,0xb6fcb85a,0xb2a4b495,0xb3c6b564,0xab26b031,0xac2bb0e4,0x2df824c3,0x2ef6258c,0x33e43168,0x34a13252,0x3697353c,0x37d4362d,0x38ca3803,0x39d038d0,
0xb880b957,0xb96bba84,0xb609b777,0xb720b872,0xb2c8b4af,0xb3ebb57e,0xab4cb047,0xac3db0fb,0x2e1824dc,0x2f1625a5,0x34083185,0x34b7326f,0x36bd355a,0x37fd364c,0x38e9381c,0x39f338eb,
0xb89cb97a,0xb98abaad,0xb62bb7a4,0xb744b88a,0xb2ecb4c9,0xb408b599,0xab72b05d,0xac50b111,0x2e3724f5,0x2f3625bf,0x341e31a2,0x34ce328d,0x36e43577,0x3813366b,0x39093835,0x3a173906,
0xb8b9b99e,0xb9aabad7,0xb64db7d0,0xb768b8a2,0xb310b4e2,0xb41ab5b3,0xab98b074,0xac63b128,0x2e57250f,0x2f5525d8,0x343331c0,0x34e432aa,0x370b3595,0x3828368a,0x3929384e,0x3a3b3922,
0xb8d6b9c3,0xb9cabb02,0xb670b7fd,0xb78cb8ba,0xb335b4fc,0xb42db5ce,0xabbeb08a,0xac76b13e,0x2e772528,0x2f7525f1,0x344931dd,0x34fa32c8,0x373335b3,0x383d36a9,0x39493868,0x3a60393e,
0xb8f3b9e8,0xb9ebbb2d,0xb693b815,0xb7b1b8d2,0xb359b516,0xb43fb5e9,0xabe3b0a1,0xac89b155,0x2e972541,0x2f95260a,0x345f31fa,0x351132e5,0x375b35d2,0x385236c8,0x396a3881,0x3a86395a,
0xb910ba0e,0xba0cbb59,0xb6b6b82c,0xb7d6b8eb,0xb37db530,0xb452b604,0xac05b0b7,0xac9cb16b,0x2eb6255a,0x2fb52623,0x34753217,0x35273303,0x378335f0,0x386836e8,0x398c389b,0x3aac3977,
0xb92eba35,0xba2dbb87,0xb6d9b843,0xb7fbb904,0xb3a2b54a,0xb464b61e,0xac18b0ce,0xacafb182,0x2ed62573,0x2fd5263c,0x348b3235,0x353e3321,0x37ab360e,0x387d3708,0x39ae38b6,0x3ad33994,
0x9ce99db2,0xad3aae11,0x9aad9c20,0xab1aac63,0x9712991b,0xa783a96d,0x8a4893db,0x9aada42c,0x157f10b6,0x25d82102,0x19e41852,0x2a432897,0x1c841b76,0x2ccf2bf0,0x1e161d4d,0x2e7d2da6,
0xa35da445,0xadd8aec9,0xa102a22f,0xabf0ace8,0x9d4d9fa8,0xa833aa11,0x90b699e4,0x9b76a4aa,0x1c201712,0x26882199,0x206b1e7b,0x2b002922,0x22c62199,0x2d602c70,0x249123f4,0x2f422e51,
0xa623a71f,0xae77af82,0xa42ca528,0xac63ad6d,0xa06ba262,0xa8a4aab5,0x93db9ce9,0x9c20a528,0x1edf19e4,0x2738222f,0x235d2166,0x2bbe29ac,0x25a524aa,0x2df22ce8,0x279c26a1,0x30042efc,
0xa84ca8fc,0xaf16b01d,0xa5d8a738,0xaccfadf2,0xa22fa478,0xa915ab59,0x957f9edf,0x9c84a5a5,0x20d01c20,0x27e822c6,0x2528238f,0x2c3d2a37,0x27e82688,0x2e842d60,0x295428a4,0x30672fa8,
0xa987aa69,0xafb5b07a,0xa783a8a4,0xad3aae77,0xa3f4a5bf,0xa987abfd,0x9712a06b,0x9ce9a623,0x222f1d4d,0x284c235d,0x26a124dc,0x2c9c2ac1,0x29152833,0x2f162dd8,0x2adb29f8,0x30ca302a,
0xaac1abd7,0xb02ab0d7,0xa897a9ac,0xada6aefc,0xa4dca705,0xa9f8ac50,0x9852a166,0x9d4da6a1,0x238f1e7b,0x28a423f4,0x280d25f1,0x2cfb2b4c,0x2a372922,0x2fa82e51,0x2c312b4c,0x312e3081,
0xabfdaca2,0xb07ab135,0xa96daab5,0xae11af82,0xa5bfa826,0xaa69aca2,0x991ba262,0x9db2a71f,0x24781fa8,0x28fc2445,0x28ca2705,0x2d5a2bd7,0x2b592a11,0x301d2ec9,0x2cf52c50,0x319230d7,
0xac9cad5a,0xb0cab192,0xaa43abbe,0xae7db004,0xa6a1a8ca,0xaadbacf5,0x99e4a35d,0x9e16a79c,0x2528206b,0x29542491,0x2987280d,0x2db92c31,0x2c3d2b00,0x30672f42,0x2db92cfb,0x31f7312e,
0xb11bb1f0,0xb3a8b479,0xaee9b047,0xb128b266,0xab4cad47,0xad6dafdb,0x9e7ba80d,0xa0d0aa05,0x29ac24dc,0x2c372738,0x2e182c76,0x308a2ea3,0x30b12fbb,0x330631c6,0x325c3185,0x34cc3426,
0xb16bb24f,0xb3fcb4aa,0xaf55b08a,0xb15fb2aa,0xabbead99,0xada6b017,0x9edfa84c,0xa102aa43,0x2a052528,0x2c632783,0x2e772cbc,0x30ba2ee9,0x30fb301a,0x33523204,0x32c131dd,0x35013453,
0xb1bcb2ae,0xb428b4db,0xafc2b0ce,0xb196b2ef,0xac18adeb,0xaddfb041,0x9f44a88b,0xa134aa82,0x2a5d2573,0x2c9027cf,0x2ed62d01,0x30eb2f2f,0x31453057,0x339e3242,0x33273235,0x35373481,
0xb20eb30d,0xb452b50d,0xb017b111,0xb1cdb335,0xac50ae3e,0xae18b06a,0x9fa8a8ca,0xa166aac1,0x2ab525bf,0x2cbc280d,0x2f362d47,0x311b2f75,0x318f3094,0x33eb3280,0x338e328d,0x356d34af,
0xb25fb36d,0xb47cb540,0xb04db155,0xb204b37a,0xac89ae90,0xae51b094,0xa006a909,0xa199ab00,0x2b0d260a,0x2ce82833,0x2f952d8c,0x314b2fbb,0x31da30d1,0x341c32be,0x33f532e5,0x35a334dd,
0xb2b1b3cd,0xb4a6b572,0xb084b199,0xb23bb3c0,0xacc2aee3,0xae8ab0be,0xa039a948,0xa1cbab40,0x2b652655,0x2d142859,0x2ff52dd2,0x317c3001,0x3224310e,0x344332fc,0x342e333e,0x35da350c,
0xb303b417,0xb4d1b5a5,0xb0bab1dd,0xb273b403,0xacfbaf36,0xaec3b0e7,0xa06ba987,0xa1fdab7f,0x2bbe26a1,0x2d40287e,0x302a2e18,0x31ac3024,0x326f314b,0x3469333b,0x34633398,0x3612353a,
0xb356b448,0xb4fcb5d9,0xb0f1b221,0xb2aab426,0xad34af88,0xaefcb111,0xa09da9c6,0xa22fabbe,0x2c0b26ec,0x2d6d28a4,0x305a2e5e,0x31dd3047,0x32bb3189,0x3490337a,0x349733f2,0x364a3569,
0xb527b60d,0xb68bb7bd,0xb2e2b449,0xb453b569,0xaf36b13b,0xb081b28d,0xa262abfd,0xa3f4acfb,0x2d9928ca,0x2efc29f8,0x320e306a,0x33983185,0x34b733b9,0x35f934dd,0x36823599,0x382e3722,
0xb553b641,0xb6bab7f5,0xb31ab46d,0xb470b58e,0xaf6fb165,0xb09db2b7,0xa294ac1e,0xa413ad1b,0x2dc528f0,0x2f292a1e,0x323e308d,0x33ca31a9,0x34df33f8,0x362234fe,0x36bb35c9,0x384d3755,
0xb57eb676,0xb6e8b817,0xb352b490,0xb48db5b3,0xafa8b18f,0xb0bab2e2,0xa2c6ac3d,0xa42cad3a,0x2df22915,0x2f552a43,0x326f30b1,0x33fc31cd,0x3506341c,0x364c351f,0x36f535f9,0x386d3789,
0xb5abb6ab,0xb717b834,0xb38bb4b4,0xb4aab5d9,0xafe2b1b9,0xb0d7b30d,0xa2f9ac5d,0xa445ad5a,0x2e1e293b,0x2f822a69,0x32a130d4,0x341731f0,0x352e343c,0x36763540,0x372f3629,0x388d37bd,
0xb5d7b6e0,0xb746b851,0xb3c3b4d8,0xb4c7b5fe,0xb00eb1e3,0xb0f4b338,0xa32bac7d,0xa45fad79,0x2e4b2961,0x2faf2a8f,0x32d230f7,0x34303214,0x3556345c,0x36a03561,0x376a365a,0x38ad37f1,
0xb604b717,0xb775b86f,0xb3fcb4fc,0xb4e4b624,0xb02ab20e,0xb111b363,0xa35dac9c,0xa478ad99,0x2e772987,0x2fdb2ab5,0x3303311b,0x34493238,0x357e347c,0x36ca3582,0x37a5368b,0x38ce3813,
0xb631b74d,0xb7a5b88d,0xb41ab520,0xb501b64a,0xb047b238,0xb12eb38e,0xa38facbc,0xa491adb9,0x2ea329ac,0x30042adb,0x3335313e,0x3463325c,0x35a7349c,0x36f535a3,0x37e236bd,0x38f0382e,
0xb65eb785,0xb7d6b8ab,0xb437b545,0xb51fb670,0xb064b262,0xb14bb3b9,0xa3c2acdb,0xa4aaadd8,0x2ed029d2,0x301a2b00,0x33663162,0x347c3280,0x35d034bd,0x372035c5,0x380f36ef,0x39113849,
0xb803b8ca,0xb8d0b9d0,0xb53cb697,0xb62db7d4,0xb168b3e4,0xb252b4a1,0xa4c3adf8,0xa58caef6,0x30312b26,0x30e42c2b,0x349532a4,0x356433c6,0x374c35e7,0x385a36fc,0x39343865,0x3a5c394d,
0xb81cb8e9,0xb8ebb9f3,0xb55ab6bd,0xb64cb7fd,0xb185b408,0xb26fb4b7,0xa4dcae18,0xa5a5af16,0x30472b4c,0x30fb2c3d,0x34af32c8,0x357e33eb,0x37773609,0x38723720,0x39573880,0x3a84396b,
0xb835b909,0xb906ba17,0xb577b6e4,0xb66bb813,0xb1a2b41e,0xb28db4ce,0xa4f5ae37,0xa5bfaf36,0x305d2b72,0x31112c50,0x34c932ec,0x35993408,0x37a4362b,0x388a3744,0x397a389c,0x3aad398a,
0xb84eb929,0xb922ba3b,0xb595b70b,0xb68ab828,0xb1c0b433,0xb2aab4e4,0xa50fae57,0xa5d8af55,0x30742b98,0x31282c63,0x34e23310,0x35b3341a,0x37d0364d,0x38a23768,0x399e38b9,0x3ad739aa,
0xb868b949,0xb93eba60,0xb5b3b733,0xb6a9b83d,0xb1ddb449,0xb2c8b4fa,0xa528ae77,0xa5f1af75,0x308a2bbe,0x313e2c76,0x34fc3335,0x35ce342d,0x37fd3670,0x38ba378c,0x39c338d6,0x3b0239ca,
0xb881b96a,0xb95aba86,0xb5d2b75b,0xb6c8b852,0xb1fab45f,0xb2e5b511,0xa541ae97,0xa60aaf95,0x30a12be3,0x31552c89,0x35163359,0x35e9343f,0x38153693,0x38d237b1,0x39e838f3,0x3b2d39eb,
0xb89bb98c,0xb977baac,0xb5f0b783,0xb6e8b868,0xb217b475,0xb303b527,0xa55aaeb6,0xa623afb5,0x30b72c05,0x316b2c9c,0x3530337d,0x36043452,0x382c36b6,0x38eb37d6,0x3a0e3910,0x3b593a0c,
0xb8b6b9ae,0xb994bad3,0xb60eb7ab,0xb708b87d,0xb235b48b,0xb321b53e,0xa573aed6,0xa63cafd5,0x30ce2c18,0x31822caf,0x354a33a2,0x361e3464,0x384336d9,0x390437fb,0x3a35392e,0x3b873a2d,
0x214d2216,0x319b326c,0x1f762084,0x2fe830c8,0x1c521de4,0x2c962e40,0x14b6197f,0x250229d7,0x97db8e48,0xa82c9ead,0x9d1b9b12,0xad6bab82,0xa0209ead,0xb05eaf14,0xa1b2a0e9,0xb204b131,
0x27f32890,0x3241332b,0x259826c6,0x306a3156,0x227b246b,0x2d202efb,0x1b122020,0x25982a87,0x9de494b6,0xa8aa9f76,0xa3a8a14d,0xae0eac32,0xa62fa502,0xb0e1afe8,0xa845a75d,0xb2b6b1cc,
0x2aa02b9b,0x32e733e8,0x28aa29a5,0x30e131e5,0x2566275d,0x2daa2fb6,0x1de422df,0x262f2b36,0xa0e997db,0xa927a020,0xa661a46b,0xaeb0aca2,0xa927a82c,0xb163b05e,0xab1daa22,0xb368b266,
0x2ca22d52,0x338d3452,0x2a872be6,0x31563273,0x278f2927,0x2e333039,0x202024cf,0x26c62be6,0xa2df997f,0xa9a5a084,0xa877a62f,0xaf53ad13,0xab36a9d7,0xb1e5b0c8,0xacfaac4b,0xb40cb300,
0x2df52ed6,0x341834b0,0x2c322d13,0x31cc3300,0x28dc2aa0,0x2ebd3096,0x214d262f,0x275d2c4b,0xa46b9b12,0xaa22a0e9,0xa9bea7f3,0xaff5ad84,0xaca2ab82,0xb266b131,0xae65ad84,0xb464b399,
0x2f46302c,0x346a350c,0x2d202e33,0x3241338d,0x29f02c0c,0x2f4630f3,0x227b278f,0x27f32ca2,0xa5669c52,0xaaa0a14d,0xab04a8dc,0xb04badf5,0xadaaac96,0xb2e7b19b,0xafcfaebd,0xb4bcb418,
0x304b30ed,0x34bc3568,0x2e0e2f53,0x32b6340c,0x2b042cc8,0x2fcf3150,0x23a82877,0x28452cfa,0xa6619d1b,0xab1da1b2,0xac25a9be,0xb09cae65,0xaeb0ad6b,0xb368b204,0xb09caff5,0xb512b464,
0x30f331ad,0x350c35c4,0x2efb3039,0x332b3452,0x2c0c2d84,0x302c31ad,0x246b2927,0x28902d52,0xa75d9de4,0xab9ba216,0xacc8aaa0,0xb0edaed6,0xafb6ae40,0xb3e8b26c,0xb150b096,0xb568b4b0,
0x355d361e,0x37c63867,0x339f3497,0x359836b4,0x3071320a,0x32913473,0x28dc2daa,0x2b363032,0xac0ca27b,0xae01a4cf,0xb13eaf46,0xb3bdb163,0xb434b2d5,0xb627b506,0xb5beb4fa,0xb826b73e,
0x35ac3678,0x3808388f,0x340934dd,0x35cf36f5,0x30b53266,0x32d534a0,0x29272e01,0x2b82305e,0xac4ba2df,0xae40a502,0xb18eafb6,0xb406b19b,0xb473b33d,0xb663b539,0xb612b545,0xb84cb784,
0x35fb36d0,0x382c38b7,0x34433521,0x36073736,0x30f932c2,0x331834ce,0x29722e59,0x2bcd308a,0xac89a344,0xae7ea534,0xb1dfb013,0xb42eb1d2,0xb4b3b3a5,0xb6a0b56b,0xb666b58f,0xb872b7c9,
0x36493728,0x385038de,0x347c3565,0x363e3776,0x313e331e,0x335c34fa,0x29be2eb0,0x2c0c30b5,0xacc8a3a8,0xaebda566,0xb22fb04b,0xb455b20a,0xb4f1b406,0xb6dcb59d,0xb6b9b5d8,0xb898b807,
0x3697377e,0x38743904,0x34b635a9,0x367537b6,0x3182337a,0x339f3527,0x2a092f08,0x2c3230e1,0xad07a406,0xaefba598,0xb27fb083,0xb47cb241,0xb530b43a,0xb717b5cf,0xb70cb621,0xb8bdb828,
0x36e437d4,0x3897392a,0x34ee35ed,0x36ab37f5,0x31c633d6,0x33e23554,0x2a542f5f,0x2c57310c,0xad45a439,0xaf3aa5cb,0xb2cfb0bb,0xb4a4b279,0xb56eb46d,0xb752b601,0xb75db669,0xb8e1b84a,
0x37303814,0x38b9394e,0x3527362f,0x36e1381a,0x320a3418,0x34123580,0x2aa02fb6,0x2c7d3137,0xad84a46b,0xaf78a5fd,0xb31eb0f3,0xb4cbb2b0,0xb5acb4a0,0xb78cb632,0xb7adb6b1,0xb905b86b,
0x377c383e,0x38db3972,0x355f3672,0x37173838,0x324e3446,0x343435ac,0x2aeb3007,0x2ca23163,0xadc3a49d,0xafb6a62f,0xb36eb12b,0xb4f1b2e7,0xb5eab4d4,0xb7c6b663,0xb7fdb6f8,0xb928b88b,
0x38fd3996,0x39f33a91,0x374c3857,0x3874393e,0x345535d8,0x355d3730,0x2cc8318e,0x2df532e7,0xaff5a661,0xb0f3a7f3,0xb518b31e,0xb649b46a,0xb800b694,0xb8dbb808,0xb94bb8ab,0xba45b99b,
0x391e39b8,0x3a0f3aad,0x37813875,0x388c3959,0x34763604,0x357d375a,0x2cee31b9,0x2e1a3312,0xb01aa694,0xb112a813,0xb53fb356,0xb66fb485,0xb81cb6c5,0xb8f5b81f,0xb96db8cb,0xba61b9b7,
0x393e39da,0x3a2b3ac7,0x37b63893,0x38a53974,0x3497362f,0x359d3784,0x2d1331e5,0x2e40333d,0xb039a6c6,0xb131a82c,0xb565b38d,0xb694b4a0,0xb838b6f5,0xb90fb836,0xb98eb8ea,0xba7cb9d2,
0x395e39fb,0x3a453ae0,0x37ea38b0,0x38bd398e,0x34b9365b,0x35be37ad,0x2d393210,0x2e653368,0xb058a6f8,0xb150a845,0xb58cb3c3,0xb6b9b4bc,0xb854b725,0xb928b84c,0xb9aeb909,0xba97b9ed,
0x397d3a1b,0x3a5f3af9,0x380f38cd,0x38d539a8,0x34da3686,0x35de37d7,0x2d5e323b,0x2e8b3393,0xb077a72a,0xb16fa85e,0xb5b2b3fa,0xb6deb4d7,0xb870b755,0xb941b863,0xb9ceb927,0xbab0ba07,
0x399b3a3a,0x3a793b10,0x382838ea,0x38ed39c1,0x34fa36b1,0x35fe3800,0x2d843266,0x2eb033bd,0xb096a75d,0xb18ea877,0xb5d8b418,0xb703b4f1,0xb88bb784,0xb95ab879,0xb9edb945,0xbac9ba21,
0x39b93a58,0x3a913b26,0x38423906,0x390439da,0x351b36dc,0x361e3814,0x2daa3291,0x2ed633e8,0xb0b5a78f,0xb1ada890,0xb5feb434,0xb728b50c,0xb8a6b7b3,0xb972b88f,0xba0bb962,0xbae0ba3a,
0x39d73a75,0x3aa93b3c,0x385b3922,0x391b39f2,0x353c3706,0x363e3828,0x2dcf32bc,0x2efb3409,0xb0d4a7c1,0xb1cca8aa,0xb624b44f,0xb74cb527,0xb8c1b7e2,0xb98ab8a5,0xba29b97f,0xbaf7ba52,
0x3ac03b50,0x3b5e3bcb,0x39323a0a,0x39de3ab8,0x365e383c,0x375738d7,0x2f21341f,0x302634c8,0xb1eba8c3,0xb2e1a98c,0xb770b542,0xb846b615,0xb9a2b8bb,0xba51b960,0xbb0dba6a,0xbb9cbb11,
0x3ad73b63,0x3b6e3bd6,0x39493a22,0x39f23acb,0x367d3850,0x377638ea,0x2f463434,0x303934dd,0xb20aa8dc,0xb300a9a5,0xb795b55d,0xb857b62f,0xb9b9b8d0,0xba65b974,0xbb22ba81,0xbba9bb24,
0x3aec3b75,0x3b7d3bdf,0x395f3a39,0x3a063ade,0x369d3864,0x379538fd,0x2f6c3449,0x304b34f1,0xb229a8f5,0xb31ea9be,0xb7b8b577,0xb868b649,0xb9d0b8e5,0xba79b987,0xbb36ba97,0xbbb6bb35,
0x3b013b86,0x3b8c3be7,0x39753a4f,0x3a193af0,0x36bc3878,0x37b3390f,0x2f91345e,0x305e3506,0xb247a90e,0xb33da9d7,0xb7dcb592,0xb879b663,0xb9e7b8fa,0xba8cb99a,0xbb4abaad,0xbbc2bb46,
0x3b153b96,0x3b993bee,0x398a3a65,0x3a2d3b02,0x36dc388b,0x37d13921,0x2fb63473,0x3071351b,0xb266a927,0xb35ca9f0,0xb800b5ac,0xb88ab67d,0xb9fdb90f,0xba9fb9ad,0xbb5cbac3,0xbbccbb56,
0x3b283ba5,0x3ba63bf4,0x39a03a7a,0x3a3f3b13,0x36fb389e,0x37ef3933,0x2fdc3488,0x30833530,0xb285a940,0xb37aaa09,0xb811b5c7,0xb89bb697,0xba12b924,0xbab1b9c0,0xbb6dbad7,0xbbd6bb65,
0x3b3b3bb3,0x3bb23bf9,0x39b53a8f,0x3a523b24,0x371a38b2,0x38073945,0x3001349d,0x30963545,0xb2a4a959,0xb399aa22,0xb823b5e1,0xb8abb6b1,0xba28b938,0xbac3b9d2,0xbb7ebaeb,0xbbdfbb74,
0x3b4d3bc0,0x3bbd3bfc,0x39ca3aa4,0x3a643b34,0x373938c5,0x38153957,0x301334b3,0x30a9355a,0xb2c2a972,0xb3b7aa3b,0xb834b5fb,0xb8bcb6ca,0xba3cb94c,0xbad4b9e4,0xbb8dbaff,0xbbe6bb82,
0x20e921b2,0x31313204,0x1ead2020,0x2f14305e,0x1b121d1b,0x2b822d6b,0xe4817db,0x1ead282c,0x997f94b6,0xa9d7a502,0x9de49c52,0xae40ac96,0xa0849f76,0xb0c8afe8,0xa216a14d,0xb26cb19b,
0x275d2845,0x31cc32b6,0x2502262f,0x2fe830e1,0x214d23a8,0x2c322e0e,0x14b61de4,0x1f7628aa,0xa0209b12,0xaa87a598,0xa46ba27b,0xaefbad20,0xa6c6a598,0xb156b06a,0xa890a7f3,0xb32bb241,
0x2a222b1d,0x32663368,0x282c2927,0x305e3163,0x246b2661,0x2ca22eb0,0x17db20e9,0x20202927,0xa2df9de4,0xab36a62f,0xa75da566,0xafb6adaa,0xa9a5a8aa,0xb1e5b0e1,0xab9baaa0,0xb3e8b2e7,
0x2c4b2cfa,0x3300340c,0x29d72b36,0x30c831e5,0x262f2877,0x2d132f53,0x197f22df,0x208429a5,0xa4cfa020,0xabe6a6c6,0xa927a78f,0xb039ae33,0xabe6aa87,0xb273b156,0xad52aca2,0xb452b38d,
0x2d842e65,0x33993464,0x2b822ca2,0x31313266,0x27f329be,0x2d842ff5,0x1b12246b,0x20e92a22,0xa62fa14d,0xac4ba75d,0xaaa0a8dc,0xb096aebd,0xad13ac32,0xb300b1cc,0xaed6adf5,0xb4b0b418,
0x2ebd2fcf,0x341834bc,0x2c962daa,0x319b32e7,0x28dc2b04,0x2df5304b,0x1c522566,0x214d2aa0,0xa78fa27b,0xaca2a7f3,0xac0ca9f0,0xb0f3af46,0xae33ad20,0xb38db241,0xb02caf46,0xb50cb46a,
0x2ff5309c,0x34643512,0x2d6b2eb0,0x32043368,0x29be2c25,0x2e65309c,0x1d1b2661,0x21b22b1d,0xa877a3a8,0xacfaa845,0xacc8ab04,0xb150afcf,0xaf53ae0e,0xb40cb2b6,0xb0edb04b,0xb568b4bc,
0x30963150,0x34b03568,0x2e402fb6,0x326c33e8,0x2aa02cc8,0x2ed630ed,0x1de4275d,0x22162b9b,0xa927a46b,0xad52a890,0xad84ac0c,0xb1adb02c,0xb039aefb,0xb452b32b,0xb1adb0f3,0xb5c4b50c,
0x34fa35be,0x373e3826,0x32d53434,0x35063627,0x2f46313e,0x316333bd,0x227b2c0c,0x24cf2e01,0xadaaa8dc,0xb032ab36,0xb20ab071,0xb473b291,0xb497b39f,0xb6b4b598,0xb61eb55d,0xb867b7c6,
0x35453612,0x3784384c,0x333d3473,0x35393663,0x2fb6318e,0x319b3406,0x22df2c4b,0x25022e40,0xae01a927,0xb05eab82,0xb266b0b5,0xb4a0b2d5,0xb4ddb409,0xb6f5b5cf,0xb678b5ac,0xb88fb808,
0x358f3666,0x37c93872,0x33a534b3,0x356b36a0,0x301331df,0x31d2342e,0x23442c89,0x25342e7e,0xae59a972,0xb08aabcd,0xb2c2b0f9,0xb4ceb318,0xb521b443,0xb736b607,0xb6d0b5fb,0xb8b7b82c,
0x35d836b9,0x38073898,0x340634f1,0x359d36dc,0x304b322f,0x320a3455,0x23a82cc8,0x25662ebd,0xaeb0a9be,0xb0b5ac0c,0xb31eb13e,0xb4fab35c,0xb565b47c,0xb776b63e,0xb728b649,0xb8deb850,
0x3621370c,0x382838bd,0x343a3530,0x35cf3717,0x3083327f,0x3241347c,0x24062d07,0x25982efb,0xaf08aa09,0xb0e1ac32,0xb37ab182,0xb527b39f,0xb5a9b4b6,0xb7b6b675,0xb77eb697,0xb904b874,
0x3669375d,0x384a38e1,0x346d356e,0x36013752,0x30bb32cf,0x327934a4,0x24392d45,0x25cb2f3a,0xaf5faa54,0xb10cac57,0xb3d6b1c6,0xb554b3e2,0xb5edb4ee,0xb7f5b6ab,0xb7d4b6e4,0xb92ab897,
0x36b137ad,0x386b3905,0x34a035ac,0x3632378c,0x30f3331e,0x32b034cb,0x246b2d84,0x25fd2f78,0xafb6aaa0,0xb137ac7d,0xb418b20a,0xb580b412,0xb62fb527,0xb81ab6e1,0xb814b730,0xb94eb8b9,
0x36f837fd,0x388b3928,0x34d435ea,0x366337c6,0x312b336e,0x32e734f1,0x249d2dc3,0x262f2fb6,0xb007aaeb,0xb163aca2,0xb446b24e,0xb5acb434,0xb672b55f,0xb838b717,0xb83eb77c,0xb972b8db,
0x38ab394b,0x399b3a45,0x36943800,0x380838db,0x331e3518,0x346a3649,0x26612ff5,0x27f330f3,0xb18eacc8,0xb2e7adf5,0xb5d8b455,0xb730b55d,0xb857b74c,0xb93eb874,0xb996b8fd,0xba91b9f3,
0x38cb396d,0x39b73a61,0x36c5381c,0x381f38f5,0x3356353f,0x3485366f,0x2694301a,0x28133112,0xb1b9acee,0xb312ae1a,0xb604b476,0xb75ab57d,0xb875b781,0xb959b88c,0xb9b8b91e,0xbaadba0f,
0x38ea398e,0x39d23a7c,0x36f53838,0x3836390f,0x338d3565,0x34a03694,0x26c63039,0x282c3131,0xb1e5ad13,0xb33dae40,0xb62fb497,0xb784b59d,0xb893b7b6,0xb974b8a5,0xb9dab93e,0xbac7ba2b,
0x390939ae,0x39ed3a97,0x37253854,0x384c3928,0x33c3358c,0x34bc36b9,0x26f83058,0x28453150,0xb210ad39,0xb368ae65,0xb65bb4b9,0xb7adb5be,0xb8b0b7ea,0xb98eb8bd,0xb9fbb95e,0xbae0ba45,
0x392739ce,0x3a073ab0,0x37553870,0x38633941,0x33fa35b2,0x34d736de,0x272a3077,0x285e316f,0xb23bad5e,0xb393ae8b,0xb686b4da,0xb7d7b5de,0xb8cdb80f,0xb9a8b8d5,0xba1bb97d,0xbaf9ba5f,
0x394539ed,0x3a213ac9,0x3784388b,0x3879395a,0x341835d8,0x34f13703,0x275d3096,0x2877318e,0xb266ad84,0xb3bdaeb0,0xb6b1b4fa,0xb800b5fe,0xb8eab828,0xb9c1b8ed,0xba3ab99b,0xbb10ba79,
0x39623a0b,0x3a3a3ae0,0x37b338a6,0x388f3972,0x343435fe,0x350c3728,0x278f30b5,0x289031ad,0xb291adaa,0xb3e8aed6,0xb6dcb51b,0xb814b61e,0xb906b842,0xb9dab904,0xba58b9b9,0xbb26ba91,
0x397f3a29,0x3a523af7,0x37e238c1,0x38a5398a,0x344f3624,0x3527374c,0x27c130d4,0x28aa31cc,0xb2bcadcf,0xb409aefb,0xb706b53c,0xb828b63e,0xb922b85b,0xb9f2b91b,0xba75b9d7,0xbb3cbaa9,
0x3a6a3b0d,0x3b113b9c,0x38bb39a2,0x39603a51,0x35423770,0x36153846,0x28c331eb,0x298c32e1,0xb41faf21,0xb4c8b026,0xb83cb65e,0xb8d7b757,0xba0ab932,0xbab8b9de,0xbb50bac0,0xbbcbbb5e,
0x3a813b22,0x3b243ba9,0x38d039b9,0x39743a65,0x355d3795,0x362f3857,0x28dc320a,0x29a53300,0xb434af46,0xb4ddb039,0xb850b67d,0xb8eab776,0xba22b949,0xbacbb9f2,0xbb63bad7,0xbbd6bb6e,
0x3a973b36,0x3b353bb6,0x38e539d0,0x39873a79,0x357737b8,0x36493868,0x28f53229,0x29be331e,0xb449af6c,0xb4f1b04b,0xb864b69d,0xb8fdb795,0xba39b95f,0xbadeba06,0xbb75baec,0xbbdfbb7d,
0x3aad3b4a,0x3b463bc2,0x38fa39e7,0x399a3a8c,0x359237dc,0x36633879,0x290e3247,0x29d7333d,0xb45eaf91,0xb506b05e,0xb878b6bc,0xb90fb7b3,0xba4fb975,0xbaf0ba19,0xbb86bb01,0xbbe7bb8c,
0x3ac33b5c,0x3b563bcc,0x390f39fd,0x39ad3a9f,0x35ac3800,0x367d388a,0x29273266,0x29f0335c,0xb473afb6,0xb51bb071,0xb88bb6dc,0xb921b7d1,0xba65b98a,0xbb02ba2d,0xbb96bb15,0xbbeebb99,
0x3ad73b6d,0x3b653bd6,0x39243a12,0x39c03ab1,0x35c73811,0x3697389b,0x29403285,0x2a09337a,0xb488afdc,0xb530b083,0xb89eb6fb,0xb933b7ef,0xba7ab9a0,0xbb13ba3f,0xbba5bb28,0xbbf4bba6,
0x3aeb3b7e,0x3b743bdf,0x39383a28,0x39d23ac3,0x35e13823,0x36b138ab,0x295932a4,0x2a223399,0xb49db001,0xb545b096,0xb8b2b71a,0xb945b807,0xba8fb9b5,0xbb24ba52,0xbbb3bb3b,0xbbf9bbb2,
0x3aff3b8d,0x3b823be6,0x394c3a3c,0x39e43ad4,0x35fb3834,0x36ca38bc,0x297232c2,0x2a3b33b7,0xb4b3b013,0xb55ab0a9,0xb8c5b739,0xb957b815,0xbaa4b9ca,0xbb34ba64,0xbbc0bb4d,0xbbfcbbbd,
0x39b839ba,0x3a973ab5,0x39b339b5,0x3a583a78,0x39af39b1,0x3a153a37,0x39aa39ad,0x39cd39f2,0x39a639a8,0x398239a8,0x39a139a4,0x3933395b,0x399d399f,0x38e03909,0x3999399b,0x388938b5,
0xb979b972,0xb865b832,0xb986b980,0xb8c7b896,0xb994b98d,0xb924b8f6,0xb9a1b99b,0xb97db951,0xb9afb9a8,0xb9d2b9a8,0xb9bcb9b5,0xba21b9fa,0xb9c9b9c3,0xba6bba47,0xb9d6b9d0,0xbab0ba8e,
0xb9f4b9fe,0xbac7bae9,0xb9dfb9e9,0xba7ebaa3,0xb9c9b9d4,0xba2dba56,0xb9b3b9be,0xb9d6ba02,0xb99db9a8,0xb979b9a8,0xb986b992,0xb916b948,0xb970b97b,0xb8adb8e2,0xb958b964,0xb840b877,
0x39373927,0x381a37b7,0x39583948,0x38943858,0x39793969,0x390738ce,0x39993989,0x3974393e,0x39b839a8,0x39da39a8,0x39d639c7,0x3a393a0b,0x39f439e5,0x3a903a65,0x3a113a02,0x3ade3ab8,
0x3a2d3a3f,0x3af43b1a,0x3a093a1b,0x3aa23acc,0x39e339f6,0x3a453a74,0x39bc39d0,0x39df3a13,0x399439a8,0x397039a8,0x396b3980,0x38f83935,0x39413956,0x387a38ba,0x3916392b,0x37e83838,
0xb8f3b8d8,0xb79bb705,0xb929b90e,0xb85fb817,0xb95db943,0xb8eab8a6,0xb990b976,0xb96bb92b,0xb9c0b9a8,0xb9e3b9a8,0xb9f0b9d8,0xba50ba1b,0xba1dba07,0xbab3ba83,0xba49ba33,0xbb0abae0,
0xba64ba7c,0xbb1ebb46,0xba31ba4b,0xbac4baf3,0xb9fcba17,0xba5cba92,0xb9c5b9e1,0xb9e7ba23,0xb98bb9a8,0xb966b9a8,0xb94fb96d,0xb8dbb922,0xb911b930,0xb845b891,0xb8d1b8f1,0xb74eb7ee,
0x38ad3887,0x36ff364e,0x38f838d3,0x382a37ac,0x3941391d,0x38cc387c,0x39863964,0x39623918,0x39c939a8,0x39eb39a8,0x3a0939e9,0x3a673a2b,0x3a453a27,0x3ad53aa0,0x3a7e3a62,0x3b323b05,
0x3b453b6e,0x3bbc3bdd,0x3ae53b17,0x3b573b8f,0x3a733aae,0x3ac73b14,0x39f03a33,0x3a113a71,0x395d39a8,0x393739a8,0x38bc390e,0x384038bf,0x380f3867,0x365f3775,0x36af376a,0x341a3540,
0xb65fb593,0xb389b115,0xb7e8b726,0xb625b4f9,0xb8adb852,0xb830b748,0xb958b905,0xb933b8b5,0xb9f4b9a8,0xba15b9a8,0xba7eba3b,0xbad1ba78,0xbaf4babc,0xbb63bb20,0xbb57bb28,0xbbc6bb9b,
0xbb68bb91,0xbbd0bbed,0xbb04bb39,0xbb6fbba6,0xba89bac9,0xbadbbb2b,0xb9f8ba43,0xba19ba7f,0xb954b9a8,0xb92eb9a8,0xb89eb8fb,0xb820b8ab,0xb7b2b83d,0xb5ebb71b,0xb60eb6e3,0xb2deb4b1,
0x35bc34d5,0x32322f0e,0x377a369e,0x35b13469,0x388e3828,0x380f36ee,0x394f38f1,0x392938a0,0x39fc39a8,0x3a1d39a8,0x3a933a4b,0x3ae53a87,0x3b133ad6,0x3b7a3b36,0x3b783b49,0x3bd93bb1,
0x3b873baf,0x3be13bf8,0x3b213b58,0x3b853bbb,0x3a9e3ae3,0x3aee3b41,0x3a003a52,0x3a213a8e,0x394a39a8,0x392439a8,0x387f38e7,0x37fe3896,0x37423812,0x357636c1,0x356a3659,0x31853420,
0xb517b414,0xb0d7abd9,0xb70ab614,0xb53ab3ae,0xb86fb7f9,0xb7ddb693,0xb946b8dd,0xb91fb88c,0xba04b9a8,0xba25b9a8,0xbaa9ba5a,0xbaf7ba95,0xbb2fbaf0,0xbb90bb4b,0xbb96bb67,0xbbe8bbc4,
0xbba3bbc9,0xbbefbbff,0xbb3dbb74,0xbb9abbcd,0xbab3bafc,0xbb01bb55,0xba09ba62,0xba29ba9c,0xb941b9a8,0xb91bb9a8,0xb85fb8d3,0xb7bdb881,0xb6d2b7cd,0xb4ffb665,0xb4c3b5ce,0xb029b31b,
0x346f32a1,0x2ef52248,0x36993587,0x34c33288,0x385037a1,0x379b3637,0x393c38c9,0x39163877,0x3a0d39a8,0x3a2d39a8,0x3abd3a69,0x3b0a3aa3,0x3b4a3b08,0x3ba33b5f,0x3bb03b82,0x3bf43bd5,
0x3bf83c00,0x3bf93bd4,0x3bac3bdc,0x3be43bfe,0x3b133b69,0x3b543bab,0x3a313aaa,0x3a503ae0,0x391139a8,0x38ea39a8,0x377a386d,0x366b3817,0x34873608,0x313b348d,0x2d9731f4,0xad65291b,
0xac3828b6,0x2ec33365,0xb44bb160,0xb0bea57f,0xb759b5da,0xb648b45d,0xb90cb862,0xb8e5b80d,0xba35b9a8,0xba54b9a8,0xbb1bbab1,0xbb5cbae6,0xbbb5bb72,0xbbe9bbb2,0xbbfcbbe3,0xbbf5bc00,
0xbbfebbfc,0xbbefbbbc,0xbbbdbbe9,0xbbeebc00,0xbb24bb7b,0xbb63bbb9,0xba39bab8,0xba58baed,0xb907b9a8,0xb8e0b9a8,0xb737b858,0xb625b802,0xb40eb5ab,0xb042b42c,0xa9b1b0cb,0x30109a48,
0x25e4ad7e,0xb0beb475,0x33a23036,0x2f8ba3db,0x3715357c,0x360233f7,0x3902384d,0x38db37ee,0x3a3d39a8,0x3a5c39a8,0x3b2c3abf,0x3b6a3af3,0x3bc53b84,0x3bf23bc0,0x3bff3bee,0x3be93c00,
0x3c003bf4,0x3be23ba0,0x3bcc3bf3,0x3bf53bff,0x3b353b8c,0x3b713bc6,0x3a413ac6,0x3a603af9,0x38fd39a8,0x38d639a8,0x36f43842,0x35df37d8,0x3328354c,0x2e913396,0x16482f40,0xb16ca852,
0x251b304e,0x32193534,0xb2adae14,0xad972aac,0xb6d2b51d,0xb5bcb334,0xb8f8b838,0xb8d1b7c2,0xba45b9a8,0xba64b9a8,0xbb3dbacc,0xbb78baff,0xbbd3bb95,0xbbf8bbcb,0xbc00bbf7,0xbbdabbfd,
0xbbfebbe6,0xbbd2bb80,0xbbd9bbfa,0xbbfbbbfb,0xbb45bb9d,0xbb7fbbd1,0xba49bad3,0xba67bb05,0xb8f3b9a8,0xb8ccb9a8,0xb6afb82d,0xb599b7ac,0xb232b4ed,0xac9cb2d2,0x294dace7,0x32c62c83,
0xac06b1db,0xb371b5f1,0x31b62b75,0x2b43adb0,0x368d34bd,0x3576326f,0x38ee3822,0x38c73796,0x3a4d39a8,0x3a6b39a8,0x3b4c3ad9,0x3b853b0b,0x3bdf3ba4,0x3bfd3bd6,0x3bfc3bfd,0x3bc83bf8,
0x3bbd3b5a,0x3b473a99,0x3bfe3bf4,0x3bf93bbe,0x3b8b3bdb,0x3bb83bf7,0x3a6f3b11,0x3a8c3b3e,0x38c139a8,0x389939a8,0x35523780,0x343236cc,0x294d320d,0xad332de2,0xb40eaedc,0xb6a4b408,
0x346336aa,0x36f438b0,0xa6ad3004,0x2e2d3451,0xb52fb1aa,0xb40ead1a,0xb8bcb76a,0xb894b6b5,0xba73b9a8,0xba90b9a8,0xbb92bb17,0xbbbdbb43,0xbbffbbe0,0xbbf6bbf9,0xbbb2bbf0,0xbb35bbb4,
0xbba5bb30,0xbb21ba5e,0xbc00bbeb,0xbbf3bbaa,0xbb98bbe4,0xbbc2bbfb,0xba76bb1d,0xba93bb49,0xb8b7b9a8,0xb88eb9a8,0xb50bb753,0xb3d3b69e,0xa17fb147,0x2f27ac51,0x34b73099,0x37423499,
0xb50bb75e,0xb790b900,0x9cb6b12e,0xb010b4e1,0x34e730e4,0x33892b11,0x38b2373d,0x38893687,0x3a7a39a8,0x3a9739a8,0x3b9e3b22,0x3bc63b4e,0x3c003be8,0x3bef3bfd,0x3b983be5,0x3b0d3b9e,
0x3b893b02,0x3af73a1f,0x3c003bdf,0x3beb3b93,0x3ba33bec,0x3bcb3bfe,0x3a7e3b28,0x3a9b3b53,0x38ad39a8,0x388439a8,0x34c33726,0x33403670,0xa51b3080,0xb08d297f,0xb55eb1c3,0xb7ddb529,
0x35b13807,0x3815394d,0x28843257,0x31093570,0xb49fb01d,0xb2f7a7da,0xb8a8b710,0xb87fb659,0xba81b9a8,0xba9eb9a8,0xbba9bb2e,0xbbcfbb58,0xbbffbbef,0xbbe6bbff,0xbb7abbd7,0xbae1bb86,
0xbb6abad0,0xbacbb9dc,0xbbfdbbd0,0xbbe1bb79,0xbbaebbf2,0xbbd3bc00,0xba85bb33,0xbaa2bb5d,0xb8a3b9a8,0xb87ab9a8,0xb47bb6f9,0xb2adb642,0x2a7aaf72,0x3185a4b6,0x360232ea,0x383a35b6,
0xb654b85d,0xb85fb996,0xac38b37d,0xb201b5fd,0x34572eaa,0x32631e48,0x389e36e3,0x3874362b,0x3a8939a8,0x3aa539a8,0x3bb33b39,0x3bd73b62,0x3bfc3bf5,0x3bdc3c00,0x3b593bc7,0x3ab33b6b,
0x39b739b9,0x3a883aa6,0x39b239b4,0x3a483a68,0x39ae39b0,0x3a033a26,0x39a939ab,0x39bb39e0,0x39a539a7,0x396e3995,0x39a039a3,0x391e3947,0x399c399e,0x38ca38f5,0x3997399a,0x3873389f,
0xb97cb975,0xb87eb84c,0xb98ab983,0xb8deb8ae,0xb997b991,0xb93bb90d,0xb9a5b99e,0xb993b967,0xb9b2b9ab,0xb9e6b9bd,0xb9bfb9b9,0xba34ba0e,0xb9ccb9c6,0xba7dba59,0xb9d9b9d3,0xbac0ba9f,
0xb9efb9f9,0xbab6bad9,0xb9d9b9e4,0xba6aba91,0xb9c4b9cf,0xba18ba42,0xb9aeb9b9,0xb9bfb9ec,0xb997b9a3,0xb961b991,0xb981b98c,0xb8fcb92f,0xb96ab975,0xb892b8c8,0xb953b95e,0xb824b85c,
0x3940392f,0x383937f6,0x39613950,0x38b13876,0x39813971,0x392338eb,0x39a03991,0x398e395a,0x39bf39b0,0x39f339c1,0x39de39cf,0x3a4f3a22,0x39fb39ec,0x3aa43a7b,0x3a183a0a,0x3af03acb,
0x3a243a36,0x3ae13b07,0x39ff3a12,0x3a8b3ab7,0x39d939ec,0x3a2c3a5d,0x39b239c6,0x39c439f9,0x398a399e,0x3953398c,0x39613975,0x38d93917,0x3936394b,0x3859389a,0x390b3921,0x37a43816,
0xb901b8e6,0xb7e6b750,0xb936b91c,0xb883b83c,0xb96ab950,0xb90bb8c8,0xb99cb983,0xb98ab94b,0xb9ccb9b4,0xb9ffb9c6,0xb9fbb9e4,0xba6aba36,0xba28ba12,0xbacaba9b,0xba53ba3e,0xbb1dbaf5,
0xba57ba70,0xbb09bb33,0xba24ba3e,0xbaabbadc,0xb9efba0a,0xba40ba77,0xb9b7b9d3,0xb9c8ba05,0xb97cb99a,0xb944b988,0xb940b95e,0xb8b6b8fe,0xb901b921,0xb81eb86b,0xb8c0b8e1,0xb6fcb79e,
0x38c0389a,0x375636a7,0x390b38e6,0x38543800,0x3953392f,0x38f238a4,0x39973975,0x3985393d,0x39d939b9,0x3a0c39ca,0x3a1839f9,0x3a843a4a,0x3a533a36,0x3aed3abb,0x3a8b3a70,0x3b473b1c,
0x3b2e3b5a,0x3ba63bce,0x3aca3afe,0x3b373b74,0x3a533a91,0x3a9d3aef,0x39cc3a12,0x39de3a42,0x39363983,0x38fc3971,0x389238e6,0x37fb3880,0x37c5383c,0x35d136eb,0x3651370d,0x330934ae,
0xb6c3b5fa,0xb460b251,0xb824b788,0xb6b8b590,0xb8d9b880,0xb873b7d5,0xb981b92f,0xb96eb8f5,0xba18b9cf,0xba48b9e0,0xba9dba5d,0xbafabaa6,0xbb0fbad9,0xbb80bb43,0xbb6cbb40,0xbbd8bbb2,
0xbb51bb7d,0xbbbdbbe0,0xbae7bb1f,0xbb4ebb8c,0xba66baa9,0xbaafbb04,0xb9d1ba1e,0xb9e2ba4e,0xb928b97e,0xb8edb96c,0xb86eb8cd,0xb7afb866,0xb74bb80b,0xb54fb684,0xb5a2b679,0xb197b411,
0x362e3549,0x338330de,0x37e6370d,0x3651350e,0x38c0385c,0x38593788,0x397c3921,0x396a38e6,0x3a2439d3,0x3a5339e4,0x3ab63a70,0x3b0f3ab7,0x3b2e3af5,0x3b973b5a,0x3b8d3b61,0x3be83bc7,
0x3b703b9c,0x3bd03bef,0x3b033b3d,0x3b653ba2,0x3a793ac1,0x3ac03b19,0x39d53a2a,0x39e63a59,0x3919397a,0x38de3967,0x384938b4,0x3761384c,0x36cf37b4,0x34cc361d,0x34f035e2,0x302332e4,
0xb596b496,0xb244aecf,0xb783b690,0xb5e8b48a,0xb8a7b836,0xb83eb73a,0xb978b912,0xb965b8d7,0xba30b9d7,0xba5fb9e8,0xbacdba82,0xbb23bac8,0xbb4cbb10,0xbbacbb6f,0xbbaabb7f,0xbbf4bbd8,
0xbb8dbbb7,0xbbe0bbf9,0xbb1dbb5a,0xbb7abbb5,0xba8bbad9,0xbad0bb2d,0xb9d9ba36,0xb9eaba65,0xb90bb975,0xb8cfb963,0xb824b89a,0xb713b831,0xb651b750,0xb447b5b3,0xb43bb549,0xad58b1a4,
0x34fc33c0,0x31032bc0,0x371e3611,0x357e3405,0x388d3811,0x382436eb,0x39733903,0x396138c8,0x3a3c39db,0x3a6a39ec,0x3ae43a94,0x3b373ad9,0x3b673b2a,0x3bbe3b83,0x3bc33b9a,0x3bfc3be7,
0x3bed3bff,0x3bff3bea,0x3b8d3bc7,0x3bcc3bf5,0x3ae13b40,0x3b1d3b83,0x39ef3a70,0x39ff3a9b,0x38c0395e,0x3883394b,0x36c33816,0x357e3750,0x33833549,0x2e84332e,0x28cf3061,0xb0aca5b2,
0xaf7ea376,0x29663166,0xb514b2fd,0xb2bfad71,0xb809b69b,0xb734b555,0xb95cb8b9,0xb949b87b,0xba75b9f1,0xbaa1ba01,0xbb49bae9,0xbb8bbb25,0xbbcfbb96,0xbbf9bbd2,0xbc00bbf2,0xbbe3bbfe,
0xbbf6bc00,0xbbfcbbda,0xbb9fbbd6,0xbbd8bbfb,0xbaf0bb52,0xbb2cbb92,0xb9f3ba7b,0xba03baa6,0xb8b1b95a,0xb873b947,0xb673b7f6,0xb52cb718,0xb276b4de,0xac5eb251,0x2052ae39,0x321f2bf2,
0x2cf4a806,0xad3fb2d8,0x34a831ee,0x31e22a93,0x37db364b,0x36fc3502,0x395738a9,0x3944386b,0x3a8039f5,0x3aab3a05,0x3b5b3af8,0x3b993b33,0x3bdd3ba7,0x3bfd3bdd,0x3bff3bfa,0x3bd13bf9,
0x3bfd3bfd,0x3bf53bc6,0x3baf3be3,0x3be23bff,0x3b003b64,0x3b393ba0,0x39f73a86,0x3a083ab0,0x38a23955,0x38633942,0x362237bf,0x34d836e0,0x31663472,0x286b3172,0xaaf82b5c,0xb390ae84,
0xa8cf2cf4,0x2fc93423,0xb43bb0de,0xb103a484,0xb7a4b5fa,0xb6c3b4ae,0xb953b89a,0xb940b85c,0xba8bb9f9,0xbab6ba0a,0xbb6cbb07,0xbba6bb40,0xbbe8bbb7,0xbc00bbe7,0xbbfabbff,0xbbbabbf1,
0xbc00bbf6,0xbbebbbae,0xbbbebbed,0xbbebbc00,0xbb0fbb74,0xbb47bbad,0xb9fbba91,0xba0cbabb,0xb892b950,0xb854b93d,0xb5d1b788,0xb484b6a7,0xb055b405,0x9248b093,0x2e6ba484,0x347e3086,
0x98b6afe2,0xb128b4d8,0x339c2f97,0x3023a420,0x376c35a8,0x368a345a,0x394e388b,0x393b384c,0x3a9639fd,0x3ac03a0e,0x3b7c3b16,0x3bb33b4d,0x3bf23bc5,0x3c003bef,0x3bf03c00,0x3ba03be5,
0x3bde3b91,0x3b8a3af7,0x3bf23bff,0x3c003be3,0x3b533bb9,0x3b823bdf,0x3a103ac5,0x3a203aec,0x38443939,0x38033925,0x342f366d,0x31b03584,0xa8392f65,0xb15a1d7f,0xb531b1c9,0xb7e0b55b,
0x3269358a,0x35a83819,0xae842a61,0x205231e2,0xb651b405,0xb567b15a,0xb936b83c,0xb923b7f6,0xbacaba12,0xbaf0ba22,0xbbbebb5a,0xbbe3bb88,0xbbfdbbf5,0xbbddbc00,0xbb81bbd6,0xbadfbb7c,
0xbbcebb70,0xbb6dbac6,0xbbf8bbfb,0xbbffbbd6,0xbb60bbc4,0xbb8dbbe7,0xba14bacf,0xba24baf5,0xb834b934,0xb7e6b921,0xb3b4b634,0xb103b549,0x2c44ada3,0x326925b2,0x35e23309,0x384135f4,
0xb3a8b63a,0xb63fb869,0x2cc2ad58,0xa89db2f0,0x3617335f,0x352c30ac,0x3931382c,0x391e37d5,0x3ad43a16,0x3afa3a26,0x3bc93b66,0x3bea3b92,0x3bf93bfa,0x3bcf3bff,0x3b5f3bc5,0x3aad3b5d,
0x3bba3b4c,0x3b4d3a93,0x3bfc3bf6,0x3bfd3bc7,0x3b6c3bce,0x3b973bed,0x3a183ad9,0x3a283afe,0x3824392f,0x37c5391c,0x330935fa,0x3055350e,0xae6b2bc0,0xb377aa61,0xb690b423,0xb890b68a,
0x347236e5,0x36d438b6,0xa9fd2f7e,0x2c1233fd,0xb5dcb2b3,0xb4f0affb,0xb92db81c,0xb919b7b4,0xbaddba1a,0xbb03ba2a,0xbbd3bb72,0xbbf0bb9c,0xbbf2bbfe,0xbbbfbbfc,0xbb38bbaf,0xba77bb3c,
0xbba4bb23,0xbb2aba5b,0xbbffbbee,0xbbfabbb6,0xbb77bbd7,0xbba1bbf3,0xba1cbae2,0xba2cbb07,0xb813b92a,0xb7a4b917,0xb25db5bf,0xaf4cb4d2,0x3048a839,0x34412cf4,0x373a34c0,0x38dc371e,
0xb50eb78e,0xb767b901,0x24e9b0d1,0xadd5b484,0x35a23207,0x34b42e9d,0x3928380b,0x39143793,0x3ae73a1e,0x3b0c3a2e,0x3bdb3b7d,0x3bf53ba6,0x3be93c00,0x3bad3bf7,0x3b0d3b97,0x3a3e3b18,
0xb999b996,0xb889b85d,0xb99db99b,0xb8e0b8b5,0xb9a1b99f,0xb933b909,0xb9a6b9a4,0xb982b95b,0xb9aab9a8,0xb9cdb9a8,0xb9afb9ad,0xba15b9f2,0xb9b3b9b1,0xba58ba37,0xb9b8b9b5,0xba97ba78,
0xb9d6b9dc,0xbab0bad0,0xb9c9b9d0,0xba6bba8e,0xb9bcb9c3,0xba21ba47,0xb9afb9b5,0xb9d2b9fa,0xb9a1b9a8,0xb97db9a8,0xb994b99b,0xb924b951,0xb986b98d,0xb8c7b8f6,0xb979b980,0xb865b896,
0x3958394d,0x38403807,0x39703964,0x38ad3877,0x3986397b,0x391638e2,0x399d3992,0x39793948,0x39b339a8,0x39d639a8,0x39c939be,0x3a2d3a02,0x39df39d4,0x3a7e3a56,0x39f439e9,0x3ac73aa3,
0x3a113a1f,0x3ade3b02,0x39f43a02,0x3a903ab8,0x39d639e5,0x3a393a65,0x39b839c7,0x39da3a0b,0x399939a8,0x397439a8,0x39793989,0x3907393e,0x39583969,0x389438ce,0x39373948,0x381a3858,
0xb916b900,0xb7e8b75e,0xb941b92b,0xb87ab838,0xb96bb956,0xb8f8b8ba,0xb994b980,0xb970b935,0xb9bcb9a8,0xb9dfb9a8,0xb9e3b9d0,0xba45ba13,0xba09b9f6,0xbaa2ba74,0xba2dba1b,0xbaf4bacc,
0xba49ba5e,0xbb0abb30,0xba1dba33,0xbab3bae0,0xb9f0ba07,0xba50ba83,0xb9c0b9d8,0xb9e3ba1b,0xb990b9a8,0xb96bb9a8,0xb95db976,0xb8eab92b,0xb929b943,0xb85fb8a6,0xb8f3b90e,0xb79bb817,
0x38d138b0,0x374e36aa,0x391138f1,0x384537ee,0x394f3930,0x38db3891,0x398b396d,0x39663922,0x39c539a8,0x39e739a8,0x39fc39e1,0x3a5c3a23,0x3a313a17,0x3ac43a92,0x3a643a4b,0x3b1e3af3,
0x3a7e3a99,0x3b323b5a,0x3a453a62,0x3ad53b05,0x3a093a27,0x3a673aa0,0x39c939e9,0x39eb3a2b,0x398639a8,0x396239a8,0x39413964,0x38cc3918,0x38f8391d,0x382a387c,0x38ad38d3,0x36ff37ac,
0xb6afb5f1,0xb41ab1db,0xb80fb76a,0xb65fb540,0xb8bcb867,0xb840b775,0xb95db90e,0xb937b8bf,0xb9f0b9a8,0xba11b9a8,0xba73ba33,0xbac7ba71,0xbae5baae,0xbb57bb14,0xbb45bb17,0xbbbcbb8f,
0xbb57bb80,0xbbc6bbe6,0xbaf4bb28,0xbb63bb9b,0xba7ebabc,0xbad1bb20,0xb9f4ba3b,0xba15ba78,0xb958b9a8,0xb933b9a8,0xb8adb905,0xb830b8b5,0xb7e8b852,0xb625b748,0xb65fb726,0xb389b4f9,
0x360e3534,0x32de304e,0x37b236e3,0x35eb34b1,0x389e383d,0x3820371b,0x395438fb,0x392e38ab,0x39f839a8,0x3a1939a8,0x3a893a43,0x3adb3a7f,0x3b043ac9,0x3b6f3b2b,0x3b683b39,0x3bd03ba6,
0x3b783ba0,0x3bd93bf4,0x3b133b49,0x3b7a3bb1,0x3a933ad6,0x3ae53b36,0x39fc3a4b,0x3a1d3a87,0x394f39a8,0x392939a8,0x388e38f1,0x380f38a0,0x377a3828,0x35b136ee,0x35bc369e,0x32323469,
0xb56ab475,0xb185ad7e,0xb742b659,0xb576b420,0xb87fb812,0xb7feb6c1,0xb94ab8e7,0xb924b896,0xba00b9a8,0xba21b9a8,0xba9eba52,0xbaeeba8e,0xbb21bae3,0xbb85bb41,0xbb87bb58,0xbbe1bbbb,
0xbb96bbbc,0xbbe8bbfc,0xbb2fbb67,0xbb90bbc4,0xbaa9baf0,0xbaf7bb4b,0xba04ba5a,0xba25ba95,0xb946b9a8,0xb91fb9a8,0xb86fb8dd,0xb7ddb88c,0xb70ab7f9,0xb53ab693,0xb517b614,0xb0d7b3ae,
0x34c33365,0x302928b6,0x36d235ce,0x34ff331b,0x385f37cd,0x37bd3665,0x394138d3,0x391b3881,0x3a0939a8,0x3a2939a8,0x3ab33a62,0x3b013a9c,0x3b3d3afc,0x3b9a3b55,0x3ba33b74,0x3bef3bcd,
0x3bb03bd4,0x3bf43c00,0x3b4a3b82,0x3ba33bd5,0x3abd3b08,0x3b0a3b5f,0x3a0d3a69,0x3a2d3aa3,0x393c39a8,0x391639a8,0x385038c9,0x379b3877,0x369937a1,0x34c33637,0x346f3587,0x2ef53288,
0xad972248,0x2d6532a1,0xb487b1f4,0xb13ba91b,0xb77ab608,0xb66bb48d,0xb911b86d,0xb8eab817,0xba31b9a8,0xba50b9a8,0xbb13baaa,0xbb54bae0,0xbbacbb69,0xbbe4bbab,0xbbf8bbdc,0xbbf9bbfe,
0xbbfcbbff,0xbbf5bbc9,0xbbb5bbe3,0xbbe9bc00,0xbb1bbb72,0xbb5cbbb2,0xba35bab1,0xba54bae6,0xb90cb9a8,0xb8e5b9a8,0xb759b862,0xb648b80d,0xb44bb5da,0xb0beb45d,0xac38b160,0x2ec3a57f,
0x29b1abd9,0xb010b414,0x340e30cb,0x30421a48,0x373735ab,0x3625342c,0x39073858,0x38e03802,0x3a3939a8,0x3a5839a8,0x3b243ab8,0x3b633aed,0x3bbd3b7b,0x3bee3bb9,0x3bfe3be9,0x3bef3c00,
0x3bff3bf8,0x3be93baf,0x3bc53bee,0x3bf23c00,0x3b2c3b84,0x3b6a3bc0,0x3a3d3abf,0x3a5c3af3,0x390239a8,0x38db39a8,0x3715384d,0x360237ee,0x33a2357c,0x2f8b33f7,0x25e43036,0xb0bea3db,
0x96482f0e,0x316c34d5,0xb328af40,0xae912852,0xb6f4b54c,0xb5dfb396,0xb8fdb842,0xb8d6b7d8,0xba41b9a8,0xba60b9a8,0xbb35bac6,0xbb71baf9,0xbbccbb8c,0xbbf5bbc6,0xbc00bbf3,0xbbe2bbff,
0xbc00bbed,0xbbdabb91,0xbbd3bbf7,0xbbf8bbfd,0xbb3dbb95,0xbb78bbcb,0xba45bacc,0xba64baff,0xb8f8b9a8,0xb8d1b9a8,0xb6d2b838,0xb5bcb7c2,0xb2adb51d,0xad97b334,0x251bae14,0x32192aac,
0xa94db115,0xb2c6b593,0x32322ce7,0x2c9cac83,0x36af34ed,0x359932d2,0x38f3382d,0x38cc37ac,0x3a4939a8,0x3a6739a8,0x3b453ad3,0x3b7f3b05,0x3bd93b9d,0x3bfb3bd1,0x3bfe3bfa,0x3bd23bfb,
0x3bfc3bdd,0x3bc83b6e,0x3bdf3bfd,0x3bfd3bf8,0x3b4c3ba4,0x3b853bd6,0x3a4d3ad9,0x3a6b3b0b,0x38ee39a8,0x38c739a8,0x368d3822,0x35763796,0x31b634bd,0x2b43326f,0xac062b75,0xb371adb0,
0x340e364e,0x36a43887,0xa94d2edc,0x2d333408,0xb552b20d,0xb432ade2,0xb8c1b780,0xb899b6cc,0xba6fb9a8,0xba8cb9a8,0xbb8bbb11,0xbbb8bb3e,0xbbfebbdb,0xbbf9bbf7,0xbbbdbbf4,0xbb47bbbe,
0xbbb2bb46,0xbb35ba7c,0xbbffbbf0,0xbbf6bbb4,0xbb92bbe0,0xbbbdbbf9,0xba73bb17,0xba90bb43,0xb8bcb9a8,0xb894b9a8,0xb52fb76a,0xb40eb6b5,0xa6adb1aa,0x2e2dad1a,0x34633004,0x36f43451,
0xb4b7b705,0xb742b8d8,0x217fb099,0xaf27b499,0x350b3147,0x33d32c51,0x38b73753,0x388e369e,0x3a7639a8,0x3a9339a8,0x3b983b1d,0x3bc23b49,0x3c003be4,0x3bf33bfb,0x3ba53beb,0x3b213baa,
0x3b983b1a,0x3b0d3a3f,0x3c003be5,0x3bef3b9e,0x3b9e3be8,0x3bc63bfd,0x3a7a3b22,0x3a973b4e,0x38b239a8,0x388939a8,0x34e7373d,0x33893687,0x9cb630e4,0xb0102b11,0xb50bb12e,0xb790b4e1,
0x355e37b7,0x37dd3927,0x251b31c3,0x308d3529,0xb4c3b080,0xb340a97f,0xb8adb726,0xb884b670,0xba7eb9a8,0xba9bb9a8,0xbba3bb28,0xbbcbbb53,0xbc00bbec,0xbbebbbfe,0xbb89bbdf,0xbaf7bb93,
0xbb7abae9,0xbae1b9fe,0xbbffbbd7,0xbbe6bb86,0xbba9bbef,0xbbcfbbff,0xba81bb2e,0xba9ebb58,0xb8a8b9a8,0xb87fb9a8,0xb49fb710,0xb2f7b659,0x2884b01d,0x3109a7da,0x35b13257,0x38153570,
0xb602b832,0xb83ab972,0xaa7ab2ea,0xb185b5b6,0x347b2f72,0x32ad24b6,0x38a336f9,0x387a3642,0x3a8539a8,0x3aa239a8,0x3bae3b33,0x3bd33b5d,0x3bfd3bf2,0x3be13c00,0x3b6a3bd0,0x3acb3b79,
0x3b593ab5,0x3ab339ba,0x3bfc3bc7,0x3bdc3b6b,0x3bb33bf5,0x3bd73c00,0x3a893b39,0x3aa53b62,0x389e39a8,0x387439a8,0x345736e3,0x3263362b,0xac382eaa,0xb2011e48,0xb654b37d,0xb85fb5fd,
0xb99ab997,0xb89fb873,0xb99eb99c,0xb8f5b8ca,0xb9a3b9a0,0xb947b91e,0xb9a7b9a5,0xb995b96e,0xb9abb9a9,0xb9e0b9bb,0xb9b0b9ae,0xba26ba03,0xb9b4b9b2,0xba68ba48,0xb9b9b9b7,0xbaa6ba88,
0xb9d3b9d9,0xba9fbac0,0xb9c6b9cc,0xba59ba7d,0xb9b9b9bf,0xba0eba34,0xb9abb9b2,0xb9bdb9e6,0xb99eb9a5,0xb967b993,0xb991b997,0xb90db93b,0xb983b98a,0xb8aeb8de,0xb975b97c,0xb84cb87e,
0x395e3953,0x385c3824,0x3975396a,0x38c83892,0x398c3981,0x392f38fc,0x39a33997,0x39913961,0x39b939ae,0x39ec39bf,0x39cf39c4,0x3a423a18,0x39e439d9,0x3a913a6a,0x39f939ef,0x3ad93ab6,
0x3a0a3a18,0x3acb3af0,0x39ec39fb,0x3a7b3aa4,0x39cf39de,0x3a223a4f,0x39b039bf,0x39c139f3,0x399139a0,0x395a398e,0x39713981,0x38eb3923,0x39503961,0x387638b1,0x392f3940,0x37f63839,
0xb921b90b,0xb816b7a4,0xb94bb936,0xb89ab859,0xb975b961,0xb917b8d9,0xb99eb98a,0xb98cb953,0xb9c6b9b2,0xb9f9b9c4,0xb9ecb9d9,0xba5dba2c,0xba12b9ff,0xbab7ba8b,0xba36ba24,0xbb07bae1,
0xba3eba53,0xbaf5bb1d,0xba12ba28,0xba9bbaca,0xb9e4b9fb,0xba36ba6a,0xb9b4b9cc,0xb9c6b9ff,0xb983b99c,0xb94bb98a,0xb950b96a,0xb8c8b90b,0xb91cb936,0xb83cb883,0xb8e6b901,0xb750b7e6,
0x38e138c0,0x379e36fc,0x39213901,0x386b381e,0x395e3940,0x38fe38b6,0x399a397c,0x39883944,0x39d339b7,0x3a0539c8,0x3a0a39ef,0x3a773a40,0x3a3e3a24,0x3adc3aab,0x3a703a57,0x3b333b09,
0x3a703a8b,0x3b1c3b47,0x3a363a53,0x3abb3aed,0x39f93a18,0x3a4a3a84,0x39b939d9,0x39ca3a0c,0x39753997,0x393d3985,0x392f3953,0x38a438f2,0x38e6390b,0x38003854,0x389a38c0,0x36a73756,
0xb70db651,0xb4aeb309,0xb83cb7c5,0xb6ebb5d1,0xb8e6b892,0xb880b7fb,0xb983b936,0xb971b8fc,0xba12b9cc,0xba42b9de,0xba91ba53,0xbaefba9d,0xbafebaca,0xbb74bb37,0xbb5abb2e,0xbbcebba6,
0xbb40bb6c,0xbbb2bbd8,0xbad9bb0f,0xbb43bb80,0xba5dba9d,0xbaa6bafa,0xb9cfba18,0xb9e0ba48,0xb92fb981,0xb8f5b96e,0xb880b8d9,0xb7d5b873,0xb788b824,0xb590b6b8,0xb5fab6c3,0xb251b460,
0x367935a2,0x34113197,0x380b374b,0x3684354f,0x38cd386e,0x386637af,0x397e3928,0x396c38ed,0x3a1e39d1,0x3a4e39e2,0x3aa93a66,0x3b043aaf,0x3b1f3ae7,0x3b8c3b4e,0x3b7d3b51,0x3be03bbd,
0x3b613b8d,0x3bc73be8,0x3af53b2e,0x3b5a3b97,0x3a703ab6,0x3ab73b0f,0x39d33a24,0x39e43a53,0x3921397c,0x38e6396a,0x385c38c0,0x37883859,0x370d37e6,0x350e3651,0x3549362e,0x30de3383,
0xb5e2b4f0,0xb2e4b023,0xb7b4b6cf,0xb61db4cc,0xb8b4b849,0xb84cb761,0xb97ab919,0xb967b8de,0xba2ab9d5,0xba59b9e6,0xbac1ba79,0xbb19bac0,0xbb3dbb03,0xbba2bb65,0xbb9cbb70,0xbbefbbd0,
0xbb7fbbaa,0xbbd8bbf4,0xbb10bb4c,0xbb6fbbac,0xba82bacd,0xbac8bb23,0xb9d7ba30,0xb9e8ba5f,0xb912b978,0xb8d7b965,0xb836b8a7,0xb73ab83e,0xb690b783,0xb48ab5e8,0xb496b596,0xaecfb244,
0x3549343b,0x31a42d58,0x37503651,0x35b33447,0x389a3824,0x38313713,0x3975390b,0x396338cf,0x3a3639d9,0x3a6539ea,0x3ad93a8b,0x3b2d3ad0,0x3b5a3b1d,0x3bb53b7a,0x3bb73b8d,0x3bf93be0,
0x3b9a3bc3,0x3be73bfc,0x3b2a3b67,0x3b833bbe,0x3a943ae4,0x3ad93b37,0x39db3a3c,0x39ec3a6a,0x39033973,0x38c83961,0x3811388d,0x36eb3824,0x3611371e,0x3405357e,0x33c034fc,0x2bc03103,
0xb061a8cf,0x25b230ac,0xb549b383,0xb32eae84,0xb816b6c3,0xb750b57e,0xb95eb8c0,0xb94bb883,0xba70b9ef,0xba9bb9ff,0xbb40bae1,0xbb83bb1d,0xbbc7bb8d,0xbbf5bbcc,0xbbffbbed,0xbbeabbff,
0xbbf2bc00,0xbbfebbe3,0xbb96bbcf,0xbbd2bbf9,0xbae9bb49,0xbb25bb8b,0xb9f1ba75,0xba01baa1,0xb8b9b95c,0xb87bb949,0xb69bb809,0xb555b734,0xb2fdb514,0xad71b2bf,0xa376af7e,0x31662966,
0x2e39a052,0xabf2b21f,0x34de3276,0x32512c5e,0x37f63673,0x3718352c,0x395a38b1,0x39473873,0x3a7b39f3,0x3aa63a03,0x3b523af0,0x3b923b2c,0x3bd63b9f,0x3bfb3bd8,0x3c003bf6,0x3bda3bfc,
0x3bfa3bff,0x3bf93bd1,0x3ba73bdd,0x3bdd3bfd,0x3af83b5b,0x3b333b99,0x39f53a80,0x3a053aab,0x38a93957,0x386b3944,0x364b37db,0x350236fc,0x31ee34a8,0x2a9331e2,0xa8062cf4,0xb2d8ad3f,
0xab5c2af8,0x2e843390,0xb472b166,0xb172a86b,0xb7bfb622,0xb6e0b4d8,0xb955b8a2,0xb942b863,0xba86b9f7,0xbab0ba08,0xbb64bb00,0xbba0bb39,0xbbe3bbaf,0xbbffbbe2,0xbbfdbbfd,0xbbc6bbf5,
0xbbffbbfa,0xbbf1bbba,0xbbb7bbe8,0xbbe7bc00,0xbb07bb6c,0xbb40bba6,0xb9f9ba8b,0xba0abab6,0xb89ab953,0xb85cb940,0xb5fab7a4,0xb4aeb6c3,0xb0deb43b,0xa484b103,0x2cf4a8cf,0x34232fc9,
0x2484ae6b,0xb086b47e,0x34053055,0x30931248,0x378835d1,0x36a73484,0x39503892,0x393d3854,0x3a9139fb,0x3abb3a0c,0x3b743b0f,0x3bad3b47,0x3bed3bbe,0x3c003beb,0x3bf63c00,0x3bae3beb,
0x3c003bf0,0x3be53ba0,0x3bc53bf2,0x3bef3c00,0x3b163b7c,0x3b4d3bb3,0x39fd3a96,0x3a0e3ac0,0x388b394e,0x384c393b,0x35a8376c,0x345a368a,0x2f97339c,0xa4203023,0xafe298b6,0xb4d8b128,
0x31c93531,0x355b37e0,0xaf652839,0x9d7f315a,0xb66db42f,0xb584b1b0,0xb939b844,0xb925b803,0xbac5ba10,0xbaecba20,0xbbb9bb53,0xbbdfbb82,0xbbffbbf2,0xbbe3bc00,0xbb91bbde,0xbaf7bb8a,
0xbbd6bb81,0xbb7cbadf,0xbbf5bbfd,0xbc00bbdd,0xbb5abbbe,0xbb88bbe3,0xba12baca,0xba22baf0,0xb83cb936,0xb7f6b923,0xb405b651,0xb15ab567,0x2a61ae84,0x31e22052,0x358a3269,0x381935a8,
0xb309b5e2,0xb5f4b841,0x2da3ac44,0xa5b2b269,0x363433b4,0x35493103,0x39343834,0x392137e6,0x3acf3a14,0x3af53a24,0x3bc43b60,0x3be73b8d,0x3bfb3bf8,0x3bd63bff,0x3b703bce,0x3ac63b6d,
0x3bc53b5f,0x3b5d3aad,0x3bfa3bf9,0x3bff3bcf,0x3b663bc9,0x3b923bea,0x3a163ad4,0x3a263afa,0x382c3931,0x37d5391e,0x335f3617,0x30ac352c,0xad582cc2,0xb2f0a89d,0xb63ab3a8,0xb869b63f,
0x34233690,0x368a3890,0xabc02e6b,0x2a613377,0xb5fab309,0xb50eb055,0xb92fb824,0xb91cb7c5,0xbad9ba18,0xbafeba28,0xbbcebb6c,0xbbedbb97,0xbbf6bbfc,0xbbc7bbfd,0xbb4cbbba,0xba93bb4d,
0xbbafbb38,0xbb3cba77,0xbbfebbf2,0xbbfcbbbf,0xbb72bbd3,0xbb9cbbf0,0xba1abadd,0xba2abb03,0xb81cb92d,0xb7b4b919,0xb2b3b5dc,0xaffbb4f0,0x2f7ea9fd,0x33fd2c12,0x36e53472,0x38b636d4,
0xb4c0b73a,0xb71eb8dc,0x2839b048,0xacf4b441,0x35bf325d,0x34d22f4c,0x392a3813,0x391737a4,0x3ae23a1c,0x3b073a2c,0x3bd73b77,0x3bf33ba1,0x3bee3bff,0x3bb63bfa,0x3b233ba4,0x3a5b3b2a,
0x3b973b0d,0x3b183a3e,0x3c003be9,0x3bf73bad,0x3b7d3bdb,0x3ba63bf5,0x3a1e3ae7,0x3a2e3b0c,0x380b3928,0x37933914,0x320735a2,0x2e9d34b4,0xb0d124e9,0xb484add5,0xb78eb50e,0xb901b767,
0xb97239ba,0x39dc3996,0xb8323ab5,0x3ad0385d,0x3927b9fe,0xba1fb94d,0x37b7bae9,0xbb02b807,0xb8d83a3f,0x3a5e3900,0xb7053b1a,0x3b30375e,0x3887ba7c,0xba99b8b0,0x364ebb46,0xbb5ab6aa,
0xb90039dc,0x3a3f3972,0xad7e3be6,0x3bf83115,0x3807ba99,0xbae9b887,0xabd9bc00,0xbbfca248,0xb5f13b30,0x3b6e3705,0x32a13bed,0x3bd4b04e,0x3365bba0,0xbbc9b4d5,0xb593bbaf,0xbb803475,
0xb88739fe,0x3a99394d,0x35f13bbc,0x3b6eb414,0x3593bb1a,0xbb80b75e,0xb8b0bb02,0xba7c37b7,0xaf0e3bc9,0x3bf43365,0x3a1f39dc,0x3927b972,0xb04ebc00,0xbbed2248,0xbb30b85d,0xb7053ab5,
0xb8073a1f,0x3ae93927,0x39fe3a3f,0x394db900,0x31dbbb80,0xbbddb593,0xbb6eb832,0xb5f13ad0,0x31153c00,0x3be62248,0x3bff32a1,0x28b6bbd4,0xb7b7bb91,0xbb023534,0xbba0304e,0x34d53bed,
0xb7053a3f,0x3b303900,0x3bbc375e,0x3414bb1a,0x2248bbc9,0xbc00b365,0xbbdda8b6,0x31db3bff,0x36aa3bd4,0x3b46b2a1,0x3a7cb64e,0xb8b0bb5a,0xba1fba5e,0xb92738d8,0xb7b739fe,0x3b02394d,
0xb5f13a5e,0x3b6e38d8,0x3bd42bd9,0xb2a1bbfc,0xb115bbf4,0xbbe6af0e,0xb9dc375e,0x39723b1a,0x39273b46,0x3a1fb6aa,0x3475bad0,0xbbafb832,0xbb91b887,0xb5343a99,0x34143c00,0x3bbc2248,
0xb4d53a7c,0x3ba038b0,0x3a3fb593,0xb900bb80,0xb534bc00,0xbb912248,0xb4143ab5,0x3bbc385d,0x3a993a5e,0x3887b8d8,0xb5f1bbfc,0xbb6e2bd9,0xbbffb475,0x28b63baf,0x3ad03a1f,0x3832b927,
0xb3653a99,0x3bc93887,0x36aab996,0xbb46b9ba,0xb7b7bbed,0xbb02304e,0x34d53bfc,0x3ba02bd9,0x3b913927,0x3534ba1f,0xbae9ba3f,0xb8073900,0xbb5a28b6,0x364e3bff,0x3bd43115,0xb2a1bbe6,
0xb1153ab5,0x3be6385d,0xa8b6bb6e,0xbbffb5f1,0xb900bbbc,0xba3f3414,0x3a1f3b30,0x3927b705,0x3bfc375e,0x2bd9bb1a,0xbbedb475,0x304e3baf,0xb9ba3593,0x39963b80,0x3887b832,0xba99bad0,
0xad7e3ad0,0x3bf83832,0xb7b7bbff,0xbb0228b6,0xb9febb6e,0xb94d35f1,0x3bed3887,0x304eba99,0x3bd43414,0xb2a1bbbc,0xb9963534,0x39ba3b91,0xb6aa3900,0x3b463a3f,0xb115bba0,0xbbe6b4d5,
0xa2483ae9,0x3c003807,0xba99bb30,0xb8873705,0xbad0bb02,0xb83237b7,0x3b462d7e,0xb6aabbf8,0x3b1a28b6,0xb75ebbff,0xaf0e3a7c,0x3bf438b0,0xabd93ab5,0x3bfc385d,0xba5ebb5a,0xb8d8364e,
0x2bd93b02,0x3bfc37b7,0xbbedb927,0xb04e3a1f,0xbb6eba7c,0xb5f138b0,0x385db6aa,0xbab5bb46,0x39dcb1db,0xb972bbdd,0x38323c00,0x3ad02248,0x34d53bbc,0x3ba03414,0xbbf4b705,0x2f0e3b30,
0x304e3b1a,0x3bed375e,0xbb91b475,0x35343baf,0xbbd4b9dc,0xb2a13972,0x2248ba7c,0xbc00b8b0,0x3832b64e,0xbad0bb5a,0x3b803a99,0x3593b887,0x39003bfc,0x3a3fabd9,0xb9273414,0x3a1f3bbc,
0x32a13b30,0x3bd43705,0xb996304e,0x39ba3bed,0xbbffb927,0xa8b63a1f,0xb832bbf4,0xbad0af0e,0x3475b8b0,0xbbafba7c,0x3ba03593,0xb4d5bb80,0x3ae93b6e,0x3807b5f1,0x2bd93a99,0x3bfc3887,
0x34753b46,0x3baf36aa,0xb4d53832,0x3ba03ad0,0xbbedb85d,0x304e3ab5,0xbb30bb5a,0xb705364e,0x2248b9fe,0xbc00b94d,0x3887b414,0xba99bbbc,0x3be63a1f,0x3115b927,0x39dc3bf4,0x3972af0e,
0x35933b5a,0x3b80364e,0x31153a99,0x3be63887,0xbba0b705,0x34d53b30,0xbbf4b8d8,0x2f0e3a5e,0xb414bb02,0xbbbcb7b7,0xabd9ba1f,0xbbfcb927,0x3bd43832,0xb2a1bad0,0x3c003972,0xa248b9dc,
0x36aa3b6e,0x3b4635f1,0x38b03bdd,0x3a7c31db,0xbb1ab534,0x375e3b91,0xba3fb04e,0x39003bed,0xb807bbaf,0xbae9b475,0xb94dbbf8,0xb9fead7e,0x3ab53365,0xb85dbbc9,0x39ba28b6,0xb996bbff,
0x37b73b80,0x3b023593,0x3b1a3bc9,0x375eb365,0xba5eb2a1,0x38d83bd4,0xb53435f1,0x3b913b6e,0xb9babbfc,0xb996abd9,0xbbddbae9,0xb1db3807,0x38b0ad7e,0xba7cbbf8,0x28b6b900,0xbbffba3f,
0x385d3b91,0x3ab53534,0x3c003a5e,0x2248b8d8,0xb972ad7e,0x39dc3bf8,0x33653a3f,0x3bc93900,0xbb02bbe6,0xb7b73115,0xbb1ab6aa,0x375e3b46,0x3414b64e,0xbbbcbb5a,0xb94dbbdd,0xb9feb1db,
0x38d83ba0,0x3a5e34d5,0x3b3037b7,0xb705bb02,0xb85d28b6,0x3ab53bff,0x39ba3be6,0x39963115,0xbbc9bb6e,0xb36535f1,0xb6aa31db,0x3b463bdd,0xaf0eb94d,0xbbf4b9fe,0xbbf8bae9,0xad7e3807,
0x394d3baf,0x39fe3475,0x38d82d7e,0xba5ebbf8,0xb64e3115,0x3b5a3be6,0x3bd43b80,0x32a1b593,0xbbffba99,0x28b63887,0x336539ba,0x3bc93996,0xb75ebae9,0xbb1ab807,0xba3fb534,0x39003b91,
0x39ba3bbc,0x39963414,0x31dbb534,0xbbddbb91,0xb3653475,0x3bc93baf,0x3b803927,0xb593ba1f,0xbba0b972,0x34d539dc,0x3a3f3be6,0x39003115,0xb9febbd4,0xb94db2a1,0xb04e35f1,0x3bed3b6e,
0x3a1f3bc9,0x39273365,0xb475b972,0xbbafb9dc,0xabd9364e,0x3bfc3b5a,0x38d831db,0xba5ebbdd,0xbab5b807,0x385d3ae9,0x3c003b30,0x2248b705,0xbb80bbf4,0xb5932f0e,0x38b03b1a,0x3a7c375e,
0x3a7c3bd4,0x38b032a1,0xb972bb5a,0xb9dcb64e,0x2f0e3807,0x3bf43ae9,0x2d7eb534,0xbbf8bb91,0xb94db4d5,0x39fe3ba0,0x3a5e37b7,0xb8d8bb02,0xbc00bb46,0x224836aa,0x3bdd3bc9,0x31dbb365,
0x3ad03bdd,0x383231db,0xbb80bc00,0xb5932248,0x347538d8,0x3baf3a5e,0xb75eb9fe,0xbb1ab94d,0xb705ad7e,0x3b303bf8,0x3414af0e,0xbbbcbbf4,0xbb6eb9dc,0x35f13972,0x3ab538b0,0xb85dba7c,
0x3b1a3be6,0x375e3115,0xbbf4bb46,0x2f0e36aa,0x37053996,0x3b3039ba,0xbae9bbd4,0xb807b2a1,0xb1db304e,0x3bdd3bed,0xb64eb94d,0xbb5ab9fe,0xb9dcb7b7,0x39723b02,0x3365ad7e,0xbbc9bbf8,
0x3b5a3bed,0x364e304e,0xbab5b94d,0x385d39fe,0x38b03a3f,0x3a7c3900,0xbbffbba0,0x28b634d5,0x2d7e3593,0x3bf83b80,0xbb02bbc9,0xb7b7b365,0xb705b1db,0x3b303bdd,0xb807b9ba,0xbae9b996,
0x3b913bf4,0x35342f0e,0xb807b4d5,0x3ae93ba0,0x39ba3ad0,0x39963832,0xba99b972,0x388739dc,0x3593385d,0x3b803ab5,0xbbe6bb6e,0x311535f1,0xad7e304e,0x3bf83bed,0xbbafbbfc,0xb475abd9,
0x3bbc3bf8,0x34142d7e,0xabd92f0e,0x3bfc3bf4,0x3a993b46,0x388736aa,0xb64eb365,0x3b5a3bc9,0x38b039ba,0x3a7c3996,0xb972b85d,0x39dc3ab5,0x34753705,0x3baf3b30,0xbb1aba5e,0x375e38d8,
0x3bdd3bfc,0x31db2bd9,0x364e3807,0x3b5a3ae9,0x3b463ba0,0x36aa34d5,0x31153475,0x3be63baf,0x3a3f3ad0,0x39003832,0xad7e28b6,0x3bf83bff,0x38d83996,0x3a5e39ba,0xb534b2a1,0x3b913bd4,
0x3bf43bff,0x2f0e28b6,0x3a1f3a7c,0x392738b0,0x3bbc3bdd,0x341431db,0x394d39ba,0x39fe3996,0x3b5a3b91,0x364e3534,0x385d38d8,0x3ab53a5e,0x3ad03b1a,0x3832375e,0x36aa37b7,0x3b463b02,
0x3bff3c00,0x28b62248,0x3bc93bd4,0x336532a1,0x3bf83bfc,0x2d7e2bd9,0x3baf3bbc,0x34753414,0x3bed3bf4,0x304e2f0e,0x3b913ba0,0x353434d5,0x3bdd3be6,0x31db3115,0x3b6e3b80,0x35f13593,
0xb5933b6e,0x3b8035f1,0xb1153bdd,0x3be631db,0x34d5bb91,0xbba0b534,0x2f0ebbed,0xbbf4b04e,0xb4143baf,0x3bbc3475,0xabd93bf8,0x3bfc2d7e,0x32a1bbc9,0xbbd4b365,0x2248bbff,0xbc00a8b6,
0x37b73b46,0x3b02b6aa,0x3b1a3832,0x375ebad0,0xb8d8bab5,0xba5e385d,0xbb91b64e,0xb5343b5a,0x39ba39fe,0x3996b94d,0x3bdd3414,0x31dbbbbc,0xba7cb927,0xb8b03a1f,0xbbffaf0e,0xa8b63bf4,
0x3bd43534,0x32a1bb91,0x39bab8d8,0xb996ba5e,0xbbffad7e,0x28b63bf8,0xb8323a3f,0x3ad03900,0x3bafb115,0xb475bbe6,0x34d5bb46,0xbba0b6aa,0xbae9364e,0x38073b5a,0xabd93bdd,0x3bfc31db,
0x3a5eb75e,0xb8d8bb1a,0xb705bbaf,0xbb303475,0xb85d39dc,0x3ab53972,0x39ba3a7c,0x3996b8b0,0x3365bb5a,0xbbc9b64e,0xbb46b887,0xb6aa3a99,0x2f0e3bfc,0x3bf42bd9,0x3bf83414,0x2d7ebbbc,
0x2bd9bbaf,0xbbfcb475,0xbbedad7e,0x304e3bf8,0x35f13be6,0x3b6eb115,0x3ab5b593,0xb85dbb80,0xb9dcba99,0xb9723887,0xb83239ba,0x3ad03996,0x3ba03807,0x34d5bae9,0x2f0ebb91,0xbbf4b534,
0xb9babae9,0xb9963807,0xb1db3b30,0x3bdd3705,0x3bc937b7,0x3365bb02,0xb593bbf8,0xbb802d7e,0xbba028b6,0x34d53bff,0x3a3f3a7c,0x3900b8b0,0x394db85d,0xb9febab5,0xbbedb64e,0xb04e3b5a,
0xbbf8b365,0x2d7e3bc9,0x3b0239dc,0x37b7b972,0x39feb64e,0xb94dbb5a,0xbbedb1db,0x304e3bdd,0xb2a13ae9,0x3bd43807,0x39bab705,0xb996bb30,0xb6aabbf4,0xbb462f0e,0xb1153b1a,0x3be6375e,
0xb8b0385d,0x3a7c3ab5,0x39dcb5f1,0xb972bb6e,0xaf0ebbbc,0xbbf4b414,0xad7e3b30,0x3bf83705,0x39fe3b1a,0x394db75e,0xb8d8bbaf,0xba5e3475,0xbc00b593,0x22483b80,0x3bdd3832,0x31dbbad0,
0x33653bdd,0x3bc931db,0xb6aabc00,0xbb462248,0xbb02ba5e,0xb7b738d8,0x3ba0394d,0x34d5b9fe,0x3b912d7e,0xb534bbf8,0xbae92f0e,0x38073bf4,0xb64e3972,0x3b5a39dc,0x32a1ba7c,0xbbd4b8b0,
0x3b1a3a7c,0x375eb8b0,0xbbf4b593,0x2f0e3b80,0xbb30a248,0x37053c00,0x3807b85d,0xbae9bab5,0x31dbba5e,0xbbddb8d8,0x364e3bfc,0x3b5a2bd9,0x39723baf,0x39dcb475,0xbbc9b927,0xb3653a1f,
0x3b6e304e,0xb5f1bbed,0xb2a139fe,0x3bd4394d,0xb1153a3f,0x3be63900,0xb9dcbba0,0xb97234d5,0xba1fbb80,0xb9273593,0x3baf3365,0xb475bbc9,0x3b9131db,0xb534bbdd,0xb41439ba,0x3bbc3996,
0x3534b900,0xbb91ba3f,0x3ae93b1a,0x3807b75e,0x39ba3bc9,0x3996b365,0xba9928b6,0x38873bff,0xbb80b2a1,0x35933bd4,0xb115bb5a,0xbbe6b64e,0x2d7eba5e,0xbbf8b8d8,0x3baf39fe,0x3475b94d,
0xb807bbf8,0xbae9ad7e,0x39feaf0e,0xb94dbbf4,0x3bdd36aa,0xb1dbbb46,0x35f13bc9,0x3b6e3365,0xb11539ba,0x3be63996,0xbbffb85d,0x28b63ab5,0xbb02bb30,0xb7b73705,0x34d5b8d8,0xbba0ba5e,
0xbbddb9fe,0xb1db394d,0xb64ebbbc,0xbb5ab414,0x36aab75e,0xbb46bb1a,0x3be637b7,0xb115bb02,0x3a3f3bc9,0x3900b365,0xad7e39dc,0x3bf83972,0xba5ea248,0x38d83c00,0xbb91bab5,0xb534385d,
0xba3fa8b6,0x39003bff,0xbbf8b8b0,0x2d7e3a7c,0xb807bbdd,0xbae9b1db,0x2bd9b9ba,0xbbfcb996,0x3b6e3534,0xb5f1bb91,0x3bd43a5e,0x32a1b8d8,0x33653b1a,0x3bc9375e,0xb59337b7,0x3b803b02,
0xa8b63996,0x3bff39ba,0xb365385d,0x3bc93ab5,0xbbf8b9fe,0xad7e394d,0xbbafbae9,0xb4753807,0x304eb900,0xbbedba3f,0x3534b75e,0xbb91bb1a,0x3bdd3a7c,0x31dbb8b0,0x3b6e3b46,0x35f1b6aa,
0x39dc3c00,0x3972a248,0x3ad03bd4,0x3832b2a1,0xb9272bd9,0x3a1f3bfc,0xb7b73414,0x3b023bbc,0xba5ebbf4,0xb8d82f0e,0xbb30bba0,0xb70534d5,0x3887b115,0xba99bbe6,0x364eb593,0xbb5abb80,
0x3bf43972,0xaf0eb9dc,0x3a1f3115,0xb927bbe6,0x34143a99,0x3bbc3887,0x39fe3c00,0x394d2248,0xbb5ab705,0x364e3b30,0xb85d304e,0x3ab53bed,0xb832bba0,0xbad0b4d5,0xbb46bbaf,0xb6aa3475,
0x3887abd9,0xba99bbfc,0xb5f1bae9,0xbb6eb807,0x3b803ba0,0x3593b4d5,0x3a7c3475,0xb8b0bbaf,0xaf0e3832,0x3bf43ad0,0x3a1f3bff,0x392728b6,0xbbedb996,0x304e39ba,0xb70532a1,0x3b303bd4,
0xb414ba1f,0xbbbcb927,0xbbfcba3f,0x2bd93900,0x3a993593,0xb887bb80,0xb64ebad0,0xbb5ab832,0x3a7c3c00,0x38b02248,0x39dc32a1,0xb972bbd4,0xb4753534,0x3baf3b91,0x3b1a3bed,0x375eb04e,
0xbb30bbf4,0xb7052f0e,0xb41434d5,0x3bbc3ba0,0x2248b832,0xbc00bad0,0xbbddb9dc,0x31db3972,0x3b46385d,0xb6aabab5,0xb8b0bb6e,0xba7cb5f1,0x3a1f3bed,0x3927304e,0x37b7abd9,0xbb02bbfc,
0xbb5ab8d8,0x364e3a5e,0x3ab53bfc,0x385d2bd9,0xba7cbbf4,0xb8b0af0e,0xa8b6375e,0x3bff3b1a,0x2d7eb6aa,0xbbf8bb46,0xbb02b832,0x37b73ad0,0x3b303887,0xb705ba99,0xbae9bc00,0xb807a248,
0xb4d53115,0x3ba03be6,0x3a3f36aa,0xb900bb46,0xbb91b996,0x353439ba,0x3bbc3bd4,0x3414b2a1,0xba99bbed,0xb887b04e,0x35f139fe,0x3b6e394d,0xa8b6b7b7,0xbbffbb02,0xb832ad7e,0x3ad03bf8,
0x38323a99,0x3ad03887,0xb593b996,0xbb80b9ba,0xb475304e,0x3baf3bed,0x375e2bd9,0xbb1abbfc,0xbb30b927,0x37053a1f,0x3bbc3a3f,0xb414b900,0xbb6ebbff,0xb5f128b6,0x3ab53be6,0x385d3115,
0x3be63bd4,0x3115b2a1,0xbbffbb5a,0x28b6364e,0x39003ae9,0x3a3f3807,0xba1fbb91,0xb927b534,0xabd934d5,0x3bfc3ba0,0xb04eb7b7,0xbbedbb02,0xb9bab6aa,0x39963b46,0x38873365,0xba99bbc9,
0x3a1f3832,0xb927bad0,0xb47528b6,0x3baf3bff,0x3bfc3b6e,0xabd9b5f1,0xba5eb887,0x38d83a99,0x3ab53bbc,0x385d3414,0xbc00bb91,0x22483534,0x35933900,0x3b803a3f,0xba7cbba0,0xb8b0b4d5,
0x2248b414,0xbc00bbbc,0x3a993b91,0x38873534,0x38323475,0xbad0bbaf,0x36aa3927,0x3b463a1f,0x3b1a39dc,0xb75eb972,0xaf0e3115,0x3bf43be6,0x3bfc3bd4,0x2bd9b2a1,0xb8d8b5f1,0x3a5e3b6e,
0xb9febb02,0xb94db7b7,0x3a5e3927,0xb8d8ba1f,0xb64eb8b0,0xbb5aba7c,0x3bd43b46,0xb2a1b6aa,0x28b6b1db,0xbbffbbdd,0x3bc93c00,0x33652248,0x375e3414,0xbb1abbbc,0x3a3f3b30,0x39003705,
0xbbedbba0,0x304e34d5,0xb534b7b7,0xbb91bb02,0xbbd4bbff,0xb2a1a8b6,0x2248b115,0xbc00bbe6,0xbad0bb6e,0xb832b5f1,0x359331db,0xbb80bbdd,0xb900b9fe,0xba3fb94d,0x39273807,0xba1fbae9,
0xb85db705,0x3ab53b30,0xbc00bbed,0x2248304e,0xb9dcb927,0x39723a1f,0xbbc9bbf4,0xb365af0e,0xbb02ba7c,0x37b738b0,0xbb1abb80,0xb75eb593,0xbbbcbb6e,0x341435f1,0xb9feba99,0xb94db887,
0x34753593,0x3baf3b80,0xb4d5b365,0x3ba03bc9,0x304e32a1,0x3bed3bd4,0xb705b5f1,0x3b303b6e,0xa2482bd9,0x3c003bfc,0xb887b807,0x3a993ae9,0xb115ad7e,0x3be63bf8,0xb972b900,0x39dc3a3f,
0x3b463b5a,0x36aa364e,0x3a7c3a99,0x38b03887,0x3b1a3b30,0x375e3705,0x3a3f3a5e,0x390038d8,0x3ae93b02,0x380737b7,0x39fe3a1f,0x394d3927,0x3ab53ad0,0x385d3832,0x39ba39dc,0x39963972,
0x28b63c00,0x3bffa248,0x33653bd4,0x3bc9b2a1,0xad7ebbfc,0xbbf82bd9,0xb475bbbc,0xbbaf3414,0x304e3bf4,0x3bedaf0e,0x35343ba0,0x3b91b4d5,0xb1dbbbe6,0xbbdd3115,0xb5f1bb80,0xbb6e3593,
0x3bf4a8b6,0xaf0ebbff,0x3a1fb8b0,0xb927ba7c,0xbbbc31db,0x34143bdd,0xb94d3996,0x39fe39ba,0x3b5ab534,0xb64ebb91,0x385dba5e,0xbab5b8d8,0xbad0375e,0x38323b1a,0xb6aa3b02,0x3b4637b7,
0xb1dbbbfc,0xbbdd2bd9,0xbb5ab807,0xb64e3ae9,0x36aa3ba0,0x3b46b4d5,0x3be63475,0x3115bbaf,0xb900bad0,0xba3f3832,0xbbf8a8b6,0x2d7e3bff,0x3a5e3996,0x38d8b9ba,0x3b91b2a1,0xb534bbd4,
0xbbbc2d7e,0x34143bf8,0x2bd93bf4,0x3bfc2f0e,0x3a99b6aa,0xb887bb46,0xb64ebbc9,0xbb5a3365,0xb8b03996,0x3a7c39ba,0x39723ab5,0x39dcb85d,0x3475bb30,0xbbafb705,0xbb1ab8d8,0xb75e3a5e,
0x35343bf4,0x3b91af0e,0x3ae9b4d5,0xb807bba0,0xb996bad0,0xb9ba3832,0xb8873972,0x3a9939dc,0x3b80385d,0x3593bab5,0x3115bb6e,0xbbe6b5f1,0xbbf8b04e,0x2d7e3bed,0x34753bfc,0x3bafabd9,
0x3b5ab04e,0xb64ebbed,0xbab5b9fe,0xb85d394d,0xb8b03900,0x3a7c3a3f,0x3bff34d5,0x28b6bba0,0x2d7ebb80,0xbbf8b593,0xbb023365,0x37b73bc9,0x37053bdd,0x3b30b1db,0x3807b996,0xbae9b9ba,
0xb75ebbe6,0xbb1a3115,0xaf0e3b46,0x3bf436aa,0x3b303996,0x3705b9ba,0xb807bbd4,0xbae932a1,0xbbddb04e,0x31db3bed,0x3b5a394d,0x364eb9fe,0x3972b7b7,0xb9dcbb02,0xbbc9ad7e,0x33653bf8,
0xbad031db,0x38323bdd,0x3b802248,0xb593bc00,0x3475ba5e,0xbbafb8d8,0xb75e394d,0x3b1a39fe,0x37053bf8,0x3b30ad7e,0xb414bbf4,0xbbbcaf0e,0xbb6eb972,0xb5f139dc,0x3ab53a7c,0x385db8b0,
0x38b03bd4,0x3a7cb2a1,0xb9dcbb5a,0xb972364e,0xbbf4b807,0xaf0e3ae9,0x3bf83534,0xad7ebb91,0x39feb4d5,0xb94dbba0,0xb8d837b7,0x3a5e3b02,0xa2483b46,0x3c0036aa,0xb1dbbbc9,0xbbddb365,
0x3a1fb365,0xb927bbc9,0xb47539dc,0x3baf3972,0x2bd93b5a,0x3bfc364e,0xb8d8bbdd,0xba5e31db,0xbab5bae9,0xb85d3807,0x3c003705,0xa248bb30,0x3b802f0e,0xb593bbf4,0xb8b0375e,0x3a7c3b1a,
0xb996bbbc,0xb9ba3414,0x3bdd3534,0xb1dbbb91,0x3bc93475,0xb365bbaf,0xb5933927,0x3b803a1f,0xb4d53972,0x3ba039dc,0xb900bbe6,0xba3f3115,0xb94dbbd4,0xb9fe32a1,0x3bed35f1,0xb04ebb6e,
0xb94d3475,0x39fe3baf,0xb8d8bbf8,0xba5e2d7e,0xb64ebbe6,0xbb5ab115,0x3bd43593,0xb2a1bb80,0x3bff3887,0x28b6ba99,0xb3653996,0x3bc939ba,0xb75e3807,0x3b1a3ae9,0xba3fbb91,0xb9003534,
0x3a5e3ba0,0x38d8b4d5,0xb70537b7,0x3b303b02,0xbab5a8b6,0x385d3bff,0xb996bbe6,0xb9ba3115,0xb365bb6e,0xbbc9b5f1,0x3b4631db,0xb6aabbdd,0x3bf4394d,0x2f0eb9fe,0x2d7e3ae9,0x3bf83807,
0x385db534,0xbab5bb91,0x3c0038d8,0xa248ba5e,0x39723bf8,0x39dcad7e,0xb3653900,0x3bc93a3f,0xbb02b115,0x37b73be6,0xbb1abb46,0xb75e36aa,0xb414bb5a,0xbbbcb64e,0x394db1db,0xb9febbdd,
0xbb02bb80,0xb7b73593,0xb75ebbc9,0xbb1ab365,0x38d8b2a1,0xba5ebbd4,0x3b9135f1,0xb534bb6e,0x39963bfc,0x39baabd9,0x31db3ae9,0x3bdd3807,0xba7cad7e,0x38b03bf8,0xbbffb900,0x28b63a3f,
0xb6aa35f1,0x3b463b6e,0xb8b031db,0x3a7c3bdd,0xbb1abb91,0xb75e3534,0xba3fbbed,0xb900304e,0x3807b475,0xbae9bbaf,0x394dad7e,0xb9febbf8,0x3ab53bc9,0x385db365,0x39ba3bff,0x3996a8b6,
0x3b803b5a,0x3593b64e,0x3be63a99,0x3115b887,0xb4d53705,0x3ba03b30,0xaf0e38d8,0x3bf43a5e,0xbbbcbb02,0xb41437b7,0xbbfcba1f,0xabd93927,0x32a1b832,0xbbd4bad0,0x2248b972,0xbc00b9dc,
0x3475b6aa,0xbbafbb46,0xb4d5bad0,0xbba0b832,0x3bed3ab5,0x304eb85d,0x3b30364e,0xb705bb5a,0x2248394d,0x3c0039fe,0x38873bbc,0x3a993414,0xbbe6b927,0x31153a1f,0xb9dcaf0e,0x39723bf4,
0xbbd4bb30,0xb2a13705,0xb9bab04e,0x39963bed,0xa8b6b927,0xbbffba1f,0xbad0bbf4,0xb8322f0e,0x3baf38b0,0xb475ba7c,0x34d5b593,0xbba0bb80,0x38073b6e,0x3ae935f1,0x3bfc3a99,0x2bd9b887,
0xb04e375e,0x3bed3b1a,0x3b913baf,0x3534b475,0xbbd4b972,0x32a139dc,0x224838b0,0x3c003a7c,0xb832bb5a,0xbad0b64e,0xbb80b887,0x35933a99,0x39002bd9,0xba3fbbfc,0xb927bbbc,0xba1fb414,
0x3bfc3b02,0x2bd9b7b7,0xb04eb927,0xbbedba1f,0x35f13a7c,0x3b6e38b0,0x3ab536aa,0xb85dbb46,0xb972b1db,0x39dc3bdd,0x3ad03c00,0x3832a248,0xbba0bbbc,0xb4d53414,0xaf0e3705,0x3bf43b30,
0xa248b807,0xbc00bae9,0xba99b705,0x38873b30,0x3ad037b7,0xb832bb02,0xbb46bbf8,0xb6aa2d7e,0x3b1a3bff,0x375ea8b6,0xaf0eb8b0,0xbbf4ba7c,0x2bd9385d,0x3bfc3ab5,0x3a5e364e,0xb8d8bb5a,
0xbbf8bad0,0x2d7e3832,0x3b023bff,0x37b728b6,0xb94dbb6e,0xb9feb5f1,0x304e3887,0x3bed3a99,0x32a1b414,0xbbd4bbbc,0xb9bab534,0x39963b91,0x3b463900,0xb6aaba3f,0xbbe6bba0,0xb11534d5,
0x3115385d,0x3be63ab5,0x28b6b5f1,0xbbffbb6e,0xb900b414,0x3a3f3bbc,0x3a1f3705,0xb927bb30,0xbbfcbb1a,0x2bd9375e,0x3bed3baf,0x304eb475,0xb9babb80,0xb996b593,0x38873ad0,0x3a993832,
0x3bc93a99,0xb365b887,0xbb46b996,0x36aa39ba,0x3b023bed,0x37b7304e,0xbba0bbfc,0xb4d52bd9,0x35343927,0x3b913a1f,0xb807ba3f,0xbae9b900,0xb64ea8b6,0x3b5a3bff,0x32a1b115,0xbbd4bbe6,
0xb4d5b8b0,0xbba0ba7c,0x3a3f3b80,0x39003593,0x35342248,0xbb91bc00,0x3414385d,0x3bbc3ab5,0x3a9938d8,0xb887ba5e,0xb5f1abd9,0x3b6e3bfc,0x3bff3baf,0x28b6b475,0xbad0b927,0x38323a1f,
0xbb6eba5e,0x35f138d8,0x32a1abd9,0xbbd4bbfc,0xbbe6bbf4,0xb1152f0e,0x3972375e,0xb9dcbb1a,0xba1fbb46,0xb927b6aa,0x3baf3ad0,0xb475b832,0xb534b887,0xbb91ba99,0x3bbc3c00,0x3414a248,
0x37053900,0x3b303a3f,0xbbbcbb1a,0x3414375e,0x22483365,0x3c003bc9,0xbbddbbff,0xb1db28b6,0xb6aab2a1,0x3b463bd4,0xba7cbb5a,0xb8b0b64e,0xba1fb8d8,0x39273a5e,0xb7b7b94d,0xbb02b9fe,
0x3ae93a1f,0xb807b927,0x394d3a3f,0x39fe3900,0x3bdd3b80,0xb1dbb593,0x35f13832,0x3b6e3ad0,0x3be63c00,0x3115a248,0x28b632a1,0x3bff3bd4,0x3b023b91,0x37b73534,0xb4d5b04e,0x3ba03bed,
0xb887b94d,0xba99b9fe,0x35f13414,0xbb6ebbbc,0xb593b75e,0xbb80bb1a,0x38b037b7,0xba7cbb02,0xaf0eb365,0xbbf4bbc9,0x3a1f3972,0xb927b9dc,0x304e2248,0xbbedbc00,0x3b303ab5,0xb705b85d,
0xba3fb9dc,0x39003972,0xbbf8bbe6,0x2d7e3115,0xbae9ba99,0x38073887,0xbbfcbc00,0xabd92248,0xbb6ebb30,0x35f13705,0xbbd4bbed,0xb2a1b04e,0xbbc9bba0,0x336534d5,0xbb80bbaf,0xb593b475,
0x39723996,0x39dc39ba,0x3832385d,0x3ad03ab5,0x3927394d,0x3a1f39fe,0x37b73807,0x3b023ae9,0x38d83900,0x3a5e3a3f,0x3705375e,0x3b303b1a,0x388738b0,0x3a993a7c,0x364e36aa,0x3b5a3b46,
0x36aa3b5a,0x3b46b64e,0x38b03a99,0x3a7cb887,0xb75ebb30,0xbb1a3705,0xb900ba5e,0xba3f38d8,0x38073b02,0x3ae9b7b7,0x394d3a1f,0x39feb927,0xb85dbad0,0xbab53832,0xb996b9dc,0xb9ba3972,
0x3475bb80,0xbbafb593,0xb4d5bbc9,0xbba03365,0xb04e3bd4,0x3bed32a1,0x37053b6e,0x3b30b5f1,0xa248bbfc,0xbc00abd9,0xb887bae9,0xba993807,0x31153bf8,0x3be6ad7e,0x39723a3f,0x39dcb900,
0xbab53705,0x385d3b30,0xa2483bed,0x3c00304e,0x3972b927,0xb9dcba1f,0xb365bbf4,0xbbc92f0e,0xb7b73a7c,0x3b0238b0,0x375e3b80,0x3b1ab593,0x3414bb6e,0xbbbcb5f1,0xb94dba99,0xb9fe3887,
0x3bed34d5,0x304ebba0,0x3534bb02,0xbb91b7b7,0xbbd428b6,0x32a13bff,0x22483be6,0x3c003115,0x3ad0b5f1,0xb832bb6e,0xb593bbdd,0xbb8031db,0xb900394d,0x3a3f39fe,0x39273ae9,0x3a1fb807,
0xb94dbb02,0xb9fe37b7,0xb8d83927,0x3a5e3a1f,0x3b5a38b0,0x364eba7c,0x32a1bb46,0xbbd4b6aa,0xbbffb1db,0x28b63bdd,0x33653c00,0x3bc9a248,0x3b1ab414,0xb75ebbbc,0xb900bb30,0xba3f3705,
0x22483bbc,0x3c003414,0x3a99b534,0xb887bb91,0xb832bbaf,0xbad03475,0xb6aa3a1f,0x3b463927,0x3b1a3972,0x375eb9dc,0xaf0ebbe6,0xbbf4b115,0xbbfcb2a1,0x2bd93bd4,0x38d83b6e,0x3a5eb5f1,
0x3927b832,0xba1fbad0,0xbbafa8b6,0x34753bff,0xabd93b6e,0x3bfc35f1,0x38d8b887,0xba5eba99,0xb85dbbbc,0xbab53414,0xa2483b91,0x3c003534,0x3b803900,0x3593ba3f,0xb8b0bba0,0xba7c34d5,
0xbbe6b2a1,0x31153bd4,0x3bff364e,0x28b6bb5a,0x3900b807,0xba3fbae9,0xba1f3534,0x39273b91,0x2bd93ba0,0x3bfc34d5,0x304ebb02,0xbbedb7b7,0xb9babb46,0xb99636aa,0x38873bc9,0x3a99b365,
0x3ad03a99,0x3832b887,0xbb80b996,0xb59339ba,0xbbafb04e,0x34753bed,0x3b1aabd9,0xb75ebbfc,0x3705b927,0xbb30ba1f,0xb4143a3f,0x3bbc3900,0x35f13bff,0x3b6e28b6,0xb85dbbe6,0xbab53115,
0xb4d5bbe6,0xbba0b115,0x3a3f3b46,0x3900b6aa,0x3b9139ba,0x3534b996,0xbbbcb2a1,0x34143bd4,0xba99304e,0x38873bed,0x35f1b94d,0xbb6eb9fe,0x28b6bb02,0xbbffb7b7,0x38323bf8,0x3ad0ad7e,
0xb64e38d8,0x3b5a3a5e,0xb85dbbfc,0xbab52bd9,0xb8b0bbf4,0xba7c2f0e,0x3bff375e,0xa8b6bb1a,0x3bf836aa,0xad7ebb46,0xb7b73832,0x3b023ad0,0xb7053887,0x3b303a99,0xb807bc00,0xbae92248,
0x3b302f0e,0xb705bbf4,0x34143ba0,0x3bbc34d5,0x22483ad0,0x3c003832,0xbbddb972,0xb1db39dc,0xbb46bab5,0xb6aa385d,0x38b0b5f1,0xba7cbb6e,0x3a1fb04e,0xb927bbed,0x37b73bfc,0x3b022bd9,
0xbbbcba1f,0xb4143927,0x2bd9ba3f,0xbbfcb900,0x3887b593,0xba99bb80,0x3b5a3ad0,0x364eb832,0x38b03c00,0x3a7ca248,0xb97232a1,0x39dc3bd4,0xbbafb534,0x34753b91,0xb75ebbed,0xbb1ab04e,
0x38873bfc,0x3a992bd9,0xb5f13807,0x3b6e3ae9,0xbb80b4d5,0x35933ba0,0xba7cbbaf,0xb8b03475,0xaf0ebad0,0xbbf4b832,0x3a1fa8b6,0xb927bbff,0x3bed39ba,0x304eb996,0x37053bd4,0x3b3032a1,
0x2f0eb972,0xbbf4b9dc,0x3927b115,0xba1fbbe6,0x3bbc3a99,0x3414b887,0x394d3c00,0x39fea248,0xb64e3705,0x3b5a3b30,0xbab5b04e,0x385d3bed,0xbad0bba0,0xb83234d5,0xb6aabbaf,0xbb46b475,
0xb9dca248,0x39723c00,0xbad0b2a1,0x38323bd4,0xb927bbfc,0xba1fabd9,0xb7b7bbbc,0xbb02b414,0x3a5e2f0e,0xb8d8bbf4,0x3b3034d5,0xb705bba0,0x38873be6,0x3a993115,0x364e3b80,0x3b5a3593,
0x3bff3996,0xa8b6b9ba,0x3bc9385d,0xb365bab5,0x2d7e39fe,0x3bf8394d,0x34753ae9,0x3baf3807,0xbbedb900,0x304e3a3f,0xbb91b75e,0x35343b1a,0xb1dbba7c,0xbbddb8b0,0xb5f1bb46,0xbb6eb6aa,
0xba3fbbff,0xb90028b6,0xbbf8ba7c,0xad7e38b0,0x3807b1db,0xbae9bbdd,0xabd9b996,0xbbfcb9ba,0x3b6e3b91,0x35f1b534,0x3bd438d8,0xb2a1ba5e,0xb365375e,0x3bc93b1a,0x35933b02,0x3b8037b7,
0x31db39fe,0x3bdd394d,0x3b5a3bbc,0x364eb414,0xbb46b75e,0x36aa3b1a,0xb11537b7,0x3be63b02,0xb900bbc9,0xba3fb365,0xbbf8b9dc,0x2d7e3972,0x38d8a248,0xba5ebc00,0xb534bab5,0xbb91b85d,
0x3807ad7e,0xbae9bbf8,0xb9febbf4,0xb94daf0e,0x3bdd3b46,0x31dbb6aa,0x35f1b365,0xbb6ebbc9,0x31153996,0x3be639ba,0x3bff3ab5,0x28b6b85d,0xbb02b705,0x37b73b30,0x34d53a5e,0x3ba038d8,
0xbb91b900,0x35343a3f,0x38073b1a,0x3ae9375e,0xb996bbc9,0xb9bab365,0xb887a8b6,0x3a993bff,0x3593b2a1,0xbb80bbd4,0xbbe6bb5a,0xb115364e,0x3bf83a5e,0xad7eb8d8,0xb475b9fe,0xbbafb94d,
0x3b6e3bed,0x35f1b04e,0xb2a1b94d,0xbbd4b9fe,0x31153900,0x3be63a3f,0x39dc34d5,0xb972bba0,0xba1fb593,0x39273b80,0x3baf3bc9,0x3475b365,0xbb91bbdd,0xb53431db,0x34143996,0x3bbc39ba,
0xb75eba7c,0xbb1ab8b0,0xaf0e3593,0x3bf43b80,0x3705a248,0xbb30bc00,0xbae9b85d,0x38073ab5,0x3bdd3a5e,0xb1dbb8d8,0xbb5abbfc,0xb64e2bd9,0x39dc3baf,0x39723475,0xb365b927,0xbbc9ba1f,
0xb36531db,0x3bc93bdd,0x36aa2248,0xbb46bc00,0xbb02b8d8,0x37b73a5e,0x3ba039fe,0xb4d5b94d,0xbb91bbf8,0xb5342d7e,0x3ae93bf4,0x38072f0e,0xb64eb9dc,0xbb5ab972,0x32a138b0,0x3bd43a7c,
0x3a7c385d,0xb8b0bab5,0xb972b5f1,0x39dc3b6e,0x3bf43bbc,0x2f0eb414,0xbbf8bb30,0x2d7e3705,0x394d3b1a,0x39fe375e,0xba5ebbaf,0xb8d8b475,0xa2483593,0x3c003b80,0xb1dbb832,0xbbddbad0,
0xbbf8bbc9,0xad7e3365,0x3b023972,0xb7b7b9dc,0xb9febb5a,0xb94db64e,0x3bed3bdd,0x304eb1db,0xb2a1b807,0xbbd4bae9,0x39ba3b30,0x39963705,0x36aa2f0e,0xbb46bbf4,0x3115375e,0x3be63b1a,
0x39963ae9,0x39ba3807,0xbbddbb30,0x31db3705,0x336537b7,0x3bc93b02,0xbb80bbf8,0xb593ad7e,0xb4d5a8b6,0x3ba03bff,0xb900ba7c,0xba3fb8b0,0xb9feb85d,0x394d3ab5,0xb04eb64e,0xbbedbb5a,
0xabd9b475,0xbbfcbbaf,0x3bed3bf8,0x304ead7e,0x35f13115,0xbb6ebbe6,0x3ab53b80,0x385d3593,0x39dc3887,0xb972ba99,0x38323996,0x3ad039ba,0x3ba03ae9,0xb4d5b807,0x2f0e3534,0x3bf43b91,
0xb8d8b75e,0x3a5e3b1a,0xbb30bbaf,0xb705b475,0xbab5b9dc,0x385d3972,0xb996ba7c,0xb9bab8b0,0xbbc9bb5a,0x3365364e,0xb6aab887,0xbb46ba99,0xbbf4bbfc,0xaf0e2bd9,0xad7eb414,0xbbf8bbbc,
0x3bd43b91,0xb2a1b534,0x39ba3a5e,0x399638d8,0x3bff3bf8,0x28b6ad7e,0x38323900,0x3ad03a3f,0x3baf3be6,0x34753115,0x34d536aa,0x3ba03b46,0x3ae93b5a,0x3807364e,0x2bd931db,0x3bfc3bdd,
0xbb02bb46,0xb7b7b6aa,0xb75eb832,0xbb1abad0,0xba5ebab5,0xb8d8b85d,0xb534b64e,0xbb91bb5a,0xb996b9fe,0xb9bab94d,0xb1dbb414,0xbbddbbbc,0xb8b0b927,0xba7cba1f,0xa8b6af0e,0xbbffbbf4,
0x359335f1,0x3b803b6e,0x311531db,0x3be63bdd,0x34d53534,0x3ba03b91,0x2f0e304e,0x3bf43bed,0x34143475,0x3bbc3baf,0x2bd92d7e,0x3bfc3bf8,0x32a13365,0x3bd43bc9,0x224828b6,0x3c003bff,
0x40000,0x60002,0xc0008,0xe000a,0x380034,0x3a0036,0x40003c,0x42003e,0x6c0068,0x6e006a,0x740070,0x760072,0xa0009c,0xa2009e,0xa800a4,0xaa00a6,
0xd400d0,0xd600d2,0xdc00d8,0xde00da,0x1080104,0x10a0106,0x110010c,0x112010e,0x13c0138,0x13e013a,0x1440140,0x1460142,0x170016c,0x172016e,0x1780174,0x17a0176,
0x1a401a0,0x1a601a2,0x1ac01a8,0x1ae01aa,0x1d801d4,0x1da01d6,0x1e001dc,0x1e201de,0x20c0208,0x20e020a,0x2140210,0x2160212,0x240023c,0x242023e,0x2480244,0x24a0246,
0x2740270,0x2760272,0x27c0278,0x27e027a,0x2a802a4,0x2aa02a6,0x2b002ac,0x2b202ae,0x2dc02d8,0x2de02da,0x2e402e0,0x2e602e2,0x310030c,0x312030e,0x3180314,0x31a0316,
0x3440340,0x3460342,0x34c0348,0x34e034a,0x3780374,0x37a0376,0x380037c,0x382037e,0x3ac03a8,0x3ae03aa,0x3b403b0,0x3b603b2,0x3e003dc,0x3e203de,0x3e803e4,0x3ea03e6,
0x4140410,0x4160412,0x41c0418,0x41e041a,0x4480444,0x44a0446,0x450044c,0x452044e,0x47c0478,0x47e047a,0x4840480,0x4860482,0x4b004ac,0x4b204ae,0x4b804b4,0x4ba04b6,
0x4e404e0,0x4e604e2,0x4ec04e8,0x4ee04ea,0x5180514,0x51a0516,0x520051c,0x522051e,0x54c0548,0x54e054a,0x5540550,0x5560552,0x580057c,0x582057e,0x5880584,0x58a0586,
0x5b405b0,0x5b605b2,0x5bc05b8,0x5be05ba,0x5e805e4,0x5ea05e6,0x5f005ec,0x5f205ee,0x61c0618,0x61e061a,0x6240620,0x6260622,0x650064c,0x652064e,0x6580654,0x65a0656,
0x140010,0x160012,0x120010,0x440012,0x480044,0x4a0046,0x460044,0x780046,0x7c0078,0x7e007a,0x7a0078,0xac007a,0xb000ac,0xb200ae,0xae00ac,0xe000ae,
0xe400e0,0xe600e2,0xe200e0,0x11400e2,0x1180114,0x11a0116,0x1160114,0x1480116,0x14c0148,0x14e014a,0x14a0148,0x17c014a,0x180017c,0x182017e,0x17e017c,0x1b0017e,
0x1b401b0,0x1b601b2,0x1b201b0,0x1e401b2,0x1e801e4,0x1ea01e6,0x1e601e4,0x21801e6,0x21c0218,0x21e021a,0x21a0218,0x24c021a,0x250024c,0x252024e,0x24e024c,0x280024e,
0x2840280,0x2860282,0x2820280,0x2b40282,0x2b802b4,0x2ba02b6,0x2b602b4,0x2e802b6,0x2ec02e8,0x2ee02ea,0x2ea02e8,0x31c02ea,0x320031c,0x322031e,0x31e031c,0x350031e,
0x3540350,0x3560352,0x3520350,0x3840352,0x3880384,0x38a0386,0x3860384,0x3b80386,0x3bc03b8,0x3be03ba,0x3ba03b8,0x3ec03ba,0x3f003ec,0x3f203ee,0x3ee03ec,0x42003ee,
0x4240420,0x4260422,0x4220420,0x4540422,0x4580454,0x45a0456,0x4560454,0x4880456,0x48c0488,0x48e048a,0x48a0488,0x4bc048a,0x4c004bc,0x4c204be,0x4be04bc,0x4f004be,
0x4f404f0,0x4f604f2,0x4f204f0,0x52404f2,0x5280524,0x52a0526,0x5260524,0x5580526,0x55c0558,0x55e055a,0x55a0558,0x58c055a,0x590058c,0x592058e,0x58e058c,0x5c0058e,
0x5c405c0,0x5c605c2,0x5c205c0,0x5f405c2,0x5f805f4,0x5fa05f6,0x5f605f4,0x62805f6,0x62c0628,0x62e062a,0x62a0628,0x65c062a,0x660065c,0x662065e,0x65e065c,0x18065e,
0x180018,0x4c001a,0x1a0018,0x4c001a,0x4c004c,0x80004e,0x4e004c,0x80004e,0x800080,0xb40082,0x820080,0xb40082,0xb400b4,0xe800b6,0xb600b4,0xe800b6,
0xe800e8,0x11c00ea,0xea00e8,0x11c00ea,0x11c011c,0x150011e,0x11e011c,0x150011e,0x1500150,0x1840152,0x1520150,0x1840152,0x1840184,0x1b80186,0x1860184,0x1b80186,
0x1b801b8,0x1ec01ba,0x1ba01b8,0x1ec01ba,0x1ec01ec,0x22001ee,0x1ee01ec,0x22001ee,0x2200220,0x2540222,0x2220220,0x2540222,0x2540254,0x2880256,0x2560254,0x2880256,
0x2880288,0x2bc028a,0x28a0288,0x2bc028a,0x2bc02bc,0x2f002be,0x2be02bc,0x2f002be,0x2f002f0,0x32402f2,0x2f202f0,0x32402f2,0x3240324,0x3580326,0x3260324,0x3580326,
0x3580358,0x38c035a,0x35a0358,0x38c035a,0x38c038c,0x3c0038e,0x38e038c,0x3c0038e,0x3c003c0,0x3f403c2,0x3c203c0,0x3f403c2,0x3f403f4,0x42803f6,0x3f603f4,0x42803f6,
0x4280428,0x45c042a,0x42a0428,0x45c042a,0x45c045c,0x490045e,0x45e045c,0x490045e,0x4900490,0x4c40492,0x4920490,0x4c40492,0x4c404c4,0x4f804c6,0x4c604c4,0x4f804c6,
0x4f804f8,0x52c04fa,0x4fa04f8,0x52c04fa,0x52c052c,0x560052e,0x52e052c,0x560052e,0x5600560,0x5940562,0x5620560,0x5940562,0x5940594,0x5c80596,0x5960594,0x5c80596,
0x5c805c8,0x5fc05ca,0x5ca05c8,0x5fc05ca,0x5fc05fc,0x63005fe,0x5fe05fc,0x63005fe,0x6300630,0x6640632,0x6320630,0x6640632,0x6640664,0x1c0666,0x6660664,0x1c0666,
0x1c001c,0x50001e,0x1e001c,0x50001e,0x500050,0x840052,0x520050,0x840052,0x840084,0xb80086,0x860084,0xb80086,0xb800b8,0xec00ba,0xba00b8,0xec00ba,
0xec00ec,0x12000ee,0xee00ec,0x12000ee,0x1200120,0x1540122,0x1220120,0x1540122,0x1540154,0x1880156,0x1560154,0x1880156,0x1880188,0x1bc018a,0x18a0188,0x1bc018a,
0x1bc01bc,0x1f001be,0x1be01bc,0x1f001be,0x1f001f0,0x22401f2,0x1f201f0,0x22401f2,0x2240224,0x2580226,0x2260224,0x2580226,0x2580258,0x28c025a,0x25a0258,0x28c025a,
0x28c028c,0x2c0028e,0x28e028c,0x2c0028e,0x2c002c0,0x2f402c2,0x2c202c0,0x2f402c2,0x2f402f4,0x32802f6,0x2f602f4,0x32802f6,0x3280328,0x35c032a,0x32a0328,0x35c032a,
0x35c035c,0x390035e,0x35e035c,0x390035e,0x3900390,0x3c40392,0x3920390,0x3c40392,0x3c403c4,0x3f803c6,0x3c603c4,0x3f803c6,0x3f803f8,0x42c03fa,0x3fa03f8,0x42c03fa,
0x42c042c,0x460042e,0x42e042c,0x460042e,0x4600460,0x4940462,0x4620460,0x4940462,0x4940494,0x4c80496,0x4960494,0x4c80496,0x4c804c8,0x4fc04ca,0x4ca04c8,0x4fc04ca,
0x4fc04fc,0x53004fe,0x4fe04fc,0x53004fe,0x5300530,0x5640532,0x5320530,0x5640532,0x5640564,0x5980566,0x5660564,0x5980566,0x5980598,0x5cc059a,0x59a0598,0x5cc059a,
0x5cc05cc,0x60005ce,0x5ce05cc,0x60005ce,0x6000600,0x6340602,0x6020600,0x6340602,0x6340634,0x6680636,0x6360634,0x6680636,0x6680668,0x20066a,0x66a0668,0x20066a,
0x5d605d6,0x60a05d6,0x5d605d6,0x60a060a,0x60a060a,0x63e063e,0x60a060a,0x63e063e,0x63e063e,0x672063e,0x63e063e,0x6720672,0x6720672,0x280028,0x6720672,0x280028,
0x5060506,0x53a0506,0x5060506,0x53a053a,0x53a053a,0x56e056e,0x53a053a,0x56e056e,0x56e056e,0x5a2056e,0x56e056e,0x5a205a2,0x5a205a2,0x5d605d6,0x5a205a2,0x5d605d6,
0x4360436,0x46a0436,0x4360436,0x46a046a,0x46a046a,0x49e049e,0x46a046a,0x49e049e,0x49e049e,0x4d2049e,0x49e049e,0x4d204d2,0x4d204d2,0x5060506,0x4d204d2,0x5060506,
0x3660366,0x39a0366,0x3660366,0x39a039a,0x39a039a,0x3ce03ce,0x39a039a,0x3ce03ce,0x3ce03ce,0x40203ce,0x3ce03ce,0x4020402,0x4020402,0x4360436,0x4020402,0x4360436,
0x2960296,0x2ca0296,0x2960296,0x2ca02ca,0x2ca02ca,0x2fe02fe,0x2ca02ca,0x2fe02fe,0x2fe02fe,0x33202fe,0x2fe02fe,0x3320332,0x3320332,0x3660366,0x3320332,0x3660366,
0x1c601c6,0x1fa01c6,0x1c601c6,0x1fa01fa,0x1fa01fa,0x22e022e,0x1fa01fa,0x22e022e,0x22e022e,0x262022e,0x22e022e,0x2620262,0x2620262,0x2960296,0x2620262,0x2960296,
0xf600f6,0x12a00f6,0xf600f6,0x12a012a,0x12a012a,0x15e015e,0x12a012a,0x15e015e,0x15e015e,0x192015e,0x15e015e,0x1920192,0x1920192,0x1c601c6,0x1920192,0x1c601c6,
0x260026,0x5a0026,0x260026,0x5a005a,0x5a005a,0x8e008e,0x5a005a,0x8e008e,0x8e008e,0xc2008e,0x8e008e,0xc200c2,0xc200c2,0xf600f6,0xc200c2,0xf600f6,
0x5d405d4,0x60805d4,0x5d405d4,0x6080608,0x6080608,0x63c063c,0x6080608,0x63c063c,0x63c063c,0x670063c,0x63c063c,0x6700670,0x6700670,0x260026,0x6700670,0x260026,
0x5040504,0x5380504,0x5040504,0x5380538,0x5380538,0x56c056c,0x5380538,0x56c056c,0x56c056c,0x5a0056c,0x56c056c,0x5a005a0,0x5a005a0,0x5d405d4,0x5a005a0,0x5d405d4,
0x4340434,0x4680434,0x4340434,0x4680468,0x4680468,0x49c049c,0x4680468,0x49c049c,0x49c049c,0x4d0049c,0x49c049c,0x4d004d0,0x4d004d0,0x5040504,0x4d004d0,0x5040504,
0x3640364,0x3980364,0x3640364,0x3980398,0x3980398,0x3cc03cc,0x3980398,0x3cc03cc,0x3cc03cc,0x40003cc,0x3cc03cc,0x4000400,0x4000400,0x4340434,0x4000400,0x4340434,
0x2940294,0x2c80294,0x2940294,0x2c802c8,0x2c802c8,0x2fc02fc,0x2c802c8,0x2fc02fc,0x2fc02fc,0x33002fc,0x2fc02fc,0x3300330,0x3300330,0x3640364,0x3300330,0x3640364,
0x1c401c4,0x1f801c4,0x1c401c4,0x1f801f8,0x1f801f8,0x22c022c,0x1f801f8,0x22c022c,0x22c022c,0x260022c,0x22c022c,0x2600260,0x2600260,0x2940294,0x2600260,0x2940294,
0xf400f4,0x12800f4,0xf400f4,0x1280128,0x1280128,0x15c015c,0x1280128,0x15c015c,0x15c015c,0x190015c,0x15c015c,0x1900190,0x1900190,0x1c401c4,0x1900190,0x1c401c4,
0x240024,0x580024,0x240024,0x580058,0x580058,0x8c008c,0x580058,0x8c008c,0x8c008c,0xc0008c,0x8c008c,0xc000c0,0xc000c0,0xf400f4,0xc000c0,0xf400f4,
0x5d205d2,0x60605d2,0x5d205d2,0x6060606,0x6060606,0x63a063a,0x6060606,0x63a063a,0x63a063a,0x66e063a,0x63a063a,0x66e066e,0x66e066e,0x240024,0x66e066e,0x240024,
0x5020502,0x5360502,0x5020502,0x5360536,0x5360536,0x56a056a,0x5360536,0x56a056a,0x56a056a,0x59e056a,0x56a056a,0x59e059e,0x59e059e,0x5d205d2,0x59e059e,0x5d205d2,
0x4320432,0x4660432,0x4320432,0x4660466,0x4660466,0x49a049a,0x4660466,0x49a049a,0x49a049a,0x4ce049a,0x49a049a,0x4ce04ce,0x4ce04ce,0x5020502,0x4ce04ce,0x5020502,
0x3620362,0x3960362,0x3620362,0x3960396,0x3960396,0x3ca03ca,0x3960396,0x3ca03ca,0x3ca03ca,0x3fe03ca,0x3ca03ca,0x3fe03fe,0x3fe03fe,0x4320432,0x3fe03fe,0x4320432,
0x2920292,0x2c60292,0x2920292,0x2c602c6,0x2c602c6,0x2fa02fa,0x2c602c6,0x2fa02fa,0x2fa02fa,0x32e02fa,0x2fa02fa,0x32e032e,0x32e032e,0x3620362,0x32e032e,0x3620362,
0x1c201c2,0x1f601c2,0x1c201c2,0x1f601f6,0x1f601f6,0x22a022a,0x1f601f6,0x22a022a,0x22a022a,0x25e022a,0x22a022a,0x25e025e,0x25e025e,0x2920292,0x25e025e,0x2920292,
0xf200f2,0x12600f2,0xf200f2,0x1260126,0x1260126,0x15a015a,0x1260126,0x15a015a,0x15a015a,0x18e015a,0x15a015a,0x18e018e,0x18e018e,0x1c201c2,0x18e018e,0x1c201c2,
0x220022,0x560022,0x220022,0x560056,0x560056,0x8a008a,0x560056,0x8a008a,0x8a008a,0xbe008a,0x8a008a,0xbe00be,0xbe00be,0xf200f2,0xbe00be,0xf200f2,
0x5d005d0,0x60405d0,0x5d005d0,0x6040604,0x6040604,0x6380638,0x6040604,0x6380638,0x6380638,0x66c0638,0x6380638,0x66c066c,0x66c066c,0x220022,0x66c066c,0x220022,
0x5000500,0x5340500,0x5000500,0x5340534,0x5340534,0x5680568,0x5340534,0x5680568,0x5680568,0x59c0568,0x5680568,0x59c059c,0x59c059c,0x5d005d0,0x59c059c,0x5d005d0,
0x4300430,0x4640430,0x4300430,0x4640464,0x4640464,0x4980498,0x4640464,0x4980498,0x4980498,0x4cc0498,0x4980498,0x4cc04cc,0x4cc04cc,0x5000500,0x4cc04cc,0x5000500,
0x3600360,0x3940360,0x3600360,0x3940394,0x3940394,0x3c803c8,0x3940394,0x3c803c8,0x3c803c8,0x3fc03c8,0x3c803c8,0x3fc03fc,0x3fc03fc,0x4300430,0x3fc03fc,0x4300430,
0x2900290,0x2c40290,0x2900290,0x2c402c4,0x2c402c4,0x2f802f8,0x2c402c4,0x2f802f8,0x2f802f8,0x32c02f8,0x2f802f8,0x32c032c,0x32c032c,0x3600360,0x32c032c,0x3600360,
0x1c001c0,0x1f401c0,0x1c001c0,0x1f401f4,0x1f401f4,0x2280228,0x1f401f4,0x2280228,0x2280228,0x25c0228,0x2280228,0x25c025c,0x25c025c,0x2900290,0x25c025c,0x2900290,
0xf000f0,0x12400f0,0xf000f0,0x1240124,0x1240124,0x1580158,0x1240124,0x1580158,0x1580158,0x18c0158,0x1580158,0x18c018c,0x18c018c,0x1c001c0,0x18c018c,0x1c001c0,
0x200020,0x540020,0x200020,0x540054,0x540054,0x880088,0x540054,0x880088,0x880088,0xbc0088,0x880088,0xbc00bc,0xbc00bc,0xf000f0,0xbc00bc,0xf000f0,
0x30003000,0x30003000,0x30003000,0x30003000,0x30003000,0x30003000,0x30003000,0x30003000,0x0,0x0,0x0,0x0,0x0,0x0,0x0,0x0,
0x30003000,0x30003000,0x30003000,0x30003000,0x30003000,0x30003000,0x30003000,0x30003000,0x0,0x0,0x0,0x0,0x0,0x0,0x0,0x0,
0x2a1f2da8,0xaf64ada8,0xaa1fada8,0x2f642da8,0x2f643000,0xaa1f0000,0xaf64b000,0x2a1f8000,0x2f642da8,0x2a1f2da8,0xaf64ada8,0xaa1fada8,0x2a1f0000,0x2f643000,0xaa1f0000,0xaf64b000,
0x263e2c72,0xafd9aea7,0xa63eac72,0x2fd92ea7,0x2ea72fd9,0xac72a63e,0xaea7afd9,0x2c72263e,0x2fd92ea7,0x263e2c72,0xafd9aea7,0xa63eac72,0x2c72263e,0x2ea72fd9,0xac72a63e,0xaea7afd9,
0x2da80000,0xada80000,0x2da88000,0xada80000,0x2da83000,0xada8b000,0x2da83000,0xada8b000,0x2da83000,0xada8b000,0x2da83000,0xada8b000,0xada80000,0x2da88000,0xada80000,0x2da88000,
0x2f642a1f,0xaf64aa1f,0x2f642a1f,0xaf64aa1f,0x2a1f2f64,0xaa1faf64,0x2a1f2f64,0xaa1faf64,0x2a1f2f64,0xaa1faf64,0x2a1f2f64,0xaa1faf64,0xaf64aa1f,0x2f642a1f,0xaf64aa1f,0x2f642a1f,
0xaa1f2da8,0x2f642da8,0x2a1fada8,0xaf64ada8,0x2f640000,0xaa1fb000,0xaf640000,0x2a1f3000,0xaf64ada8,0xaa1f2da8,0x2f642da8,0x2a1fada8,0x2a1f3000,0x2f648000,0xaa1fb000,0xaf640000,
0xaea7263e,0x2c722fd9,0x2ea7a63e,0xac72afd9,0x2fd92c72,0x263eaea7,0xafd9ac72,0xa63e2ea7,0xac72afd9,0xaea7263e,0x2c722fd9,0x2ea7a63e,0xa63e2ea7,0x2fd92c72,0x263eaea7,0xafd9ac72,
0xada82da8,0xada82da8,0xada82da8,0xada82da8,0x2da8ada8,0x2da8ada8,0x2da8ada8,0x2da8ada8,0x2da82da8,0x2da82da8,0x2da82da8,0x2da82da8,0xada8ada8,0xada8ada8,0xada8ada8,0xada8ada8,
0x3000,0x3000,0x3000,0x80003000,0x8000b000,0x8000b000,0x8000b000,0x8000b000,0x30000000,0x30008000,0x30008000,0x30008000,0xb0000000,0xb0000000,0xb0000000,0xb0000000,
0x2ea7263e,0xac722fd9,0xaea7a63e,0x2c72afd9,0xafd92c72,0xa63eaea7,0x2fd9ac72,0x263e2ea7,0x2c72afd9,0x2ea7263e,0xac722fd9,0xaea7a63e,0x263e2ea7,0xafd92c72,0xa63eaea7,0x2fd9ac72,
0x2f64ada8,0x2a1f2da8,0xaf642da8,0xaa1fada8,0xaa1f3000,0xaf640000,0x2a1fb000,0x2f648000,0xaa1fada8,0x2f64ada8,0x2a1f2da8,0xaf642da8,0x2f640000,0xaa1f3000,0xaf640000,0x2a1fb000,
0xaa1f2f64,0x2a1faf64,0xaa1f2f64,0x2a1faf64,0x2f64aa1f,0xaf642a1f,0x2f64aa1f,0xaf642a1f,0xaf642a1f,0x2f64aa1f,0xaf642a1f,0x2f64aa1f,0xaa1f2f64,0x2a1faf64,0xaa1f2f64,0x2a1faf64,
0x2da80000,0xada80000,0x2da88000,0xada80000,0x2da8b000,0xada83000,0x2da8b000,0xada83000,0xada83000,0x2da8b000,0xada83000,0x2da8b000,0x2da88000,0xada80000,0x2da88000,0xada88000,
0xa63e2c72,0x2fd9aea7,0x263eac72,0xafd92ea7,0xaea72fd9,0x2c72a63e,0x2ea7afd9,0xac72263e,0xafd92ea7,0xa63e2c72,0x2fd9aea7,0x263eac72,0xac72263e,0xaea72fd9,0x2c72a63e,0x2ea7afd9,
0x2f64ada8,0x2a1fada8,0xaf642da8,0xaa1f2da8,0x2a1f0000,0x2f64b000,0xaa1f0000,0xaf643000,0xaa1f2da8,0x2f64ada8,0x2a1fada8,0xaf642da8,0xaf643000,0x2a1f8000,0x2f64b000,0xaa1f8000,
0xb0003000,0xb0003000,0xb0003000,0xb0003000,0xb0003000,0xb0003000,0xb0003000,0xb0003000,0x0,0x8000,0x8000,0x80008000,0x8000,0x8000,0x8000,0x8000,
0x80000000,0x80000000,0x80008000,0x80008000,0x80000000,0x80008000,0x80008000,0x80008000,0xb0003000,0xb0003000,0xb0003000,0xb0003000,0xb0003000,0xb0003000,0xb0003000,0xb0003000,
0xaa1f2da8,0x2f64ada8,0x2a1fada8,0xaf642da8,0xaf643000,0x2a1f0000,0x2f64b000,0xaa1f8000,0xaf642da8,0xaa1f2da8,0x2f64ada8,0x2a1fada8,0xaa1f0000,0xaf643000,0x2a1f0000,0x2f64b000,
0x2fd9aea7,0x263eac72,0xafd92ea7,0xa63e2c72,0x2c72a63e,0x2ea7afd9,0xac72263e,0xaea72fd9,0xa63e2c72,0x2fd9aea7,0x263eac72,0xafd92ea7,0xaea72fd9,0x2c72a63e,0x2ea7afd9,0xac72263e,
0xada80000,0x2da80000,0xada88000,0x2da80000,0xada83000,0x2da8b000,0xada83000,0x2da8b000,0xada83000,0x2da8b000,0xada83000,0x2da8b000,0x2da80000,0xada88000,0x2da88000,0xada88000,
0xaa1f2f64,0x2a1faf64,0xaa1f2f64,0x2a1faf64,0x2f64aa1f,0xaf642a1f,0x2f64aa1f,0xaf642a1f,0x2f64aa1f,0xaf642a1f,0x2f64aa1f,0xaf642a1f,0x2a1faf64,0xaa1f2f64,0x2a1faf64,0xaa1f2f64,
0x2a1f2da8,0xaf642da8,0xaa1fada8,0x2f64ada8,0xaf640000,0x2a1fb000,0x2f640000,0xaa1f3000,0x2f64ada8,0x2a1f2da8,0xaf642da8,0xaa1fada8,0xaa1f3000,0xaf648000,0x2a1fb000,0x2f640000,
0x2c72afd9,0x2ea7263e,0xac722fd9,0xaea7a63e,0x263e2ea7,0xafd92c72,0xa63eaea7,0x2fd9ac72,0xaea7a63e,0x2c72afd9,0x2ea7263e,0xac722fd9,0x2fd9ac72,0x263e2ea7,0xafd92c72,0xa63eaea7,
0x2da8ada8,0x2da8ada8,0x2da8ada8,0x2da8ada8,0xada82da8,0xada82da8,0xada82da8,0xada82da8,0x2da82da8,0x2da82da8,0x2da82da8,0x2da82da8,0xada8ada8,0xada8ada8,0xada8ada8,0xada8ada8,
0x80003000,0x80003000,0x80003000,0x3000,0xb000,0x8000b000,0xb000,0xb000,0xb0000000,0xb0008000,0xb0008000,0xb0008000,0x30000000,0x30000000,0x30000000,0x30008000,
0x2c722fd9,0x2ea7a63e,0xac72afd9,0xaea7263e,0x263eaea7,0xafd9ac72,0xa63e2ea7,0x2fd92c72,0xaea7263e,0x2c722fd9,0x2ea7a63e,0xac72afd9,0x2fd92c72,0x263eaea7,0xafd9ac72,0xa63e2ea7,
0xaf64ada8,0xaa1f2da8,0x2f642da8,0x2a1fada8,0x2a1f3000,0x2f648000,0xaa1fb000,0xaf648000,0x2a1fada8,0xaf64ada8,0xaa1f2da8,0x2f642da8,0xaf640000,0x2a1f3000,0x2f648000,0xaa1fb000,
0x2f642a1f,0xaf64aa1f,0x2f642a1f,0xaf64aa1f,0x2a1f2f64,0xaa1faf64,0x2a1f2f64,0xaa1faf64,0xaa1faf64,0x2a1f2f64,0xaa1faf64,0x2a1f2f64,0x2f642a1f,0xaf64aa1f,0x2f642a1f,0xaf64aa1f,
0xada80000,0x2da80000,0xada88000,0x2da88000,0xada8b000,0x2da83000,0xada8b000,0x2da83000,0x2da83000,0xada8b000,0x2da83000,0xada8b000,0xada88000,0x2da88000,0xada88000,0x2da80000,
0x2fd92ea7,0x263e2c72,0xafd9aea7,0xa63eac72,0x2c72263e,0x2ea72fd9,0xac72a63e,0xaea7afd9,0xa63eac72,0x2fd92ea7,0x263e2c72,0xafd9aea7,0xaea7afd9,0x2c72263e,0x2ea72fd9,0xac72a63e,
0xaf64ada8,0xaa1fada8,0x2f642da8,0x2a1f2da8,0xaa1f0000,0xaf64b000,0x2a1f0000,0x2f643000,0x2a1f2da8,0xaf64ada8,0xaa1fada8,0x2f642da8,0x2f643000,0xaa1f8000,0xaf64b000,0x2a1f0000,
0x80008000,0x80008000,0x80008000,0x80008000,0x80008000,0x80008000,0x80008000,0x80008000,0x30003000,0x30003000,0x30003000,0x30003000,0x30003000,0x30003000,0x30003000,0x30003000,
0x80008000,0x80008000,0x80008000,0x80008000,0x80008000,0x80008000,0x80008000,0x80008000,0x30003000,0x30003000,0x30003000,0x30003000,0x30003000,0x30003000,0x30003000,0x30003000,
0xaf64ada8,0xaa1fada8,0x2f642da8,0x2a1f2da8,0xaa1f8000,0xaf64b000,0x2a1f8000,0x2f643000,0x2a1f2da8,0xaf64ada8,0xaa1fada8,0x2f642da8,0x2f643000,0xaa1f0000,0xaf64b000,0x2a1f8000,
0xafd9aea7,0xa63eac72,0x2fd92ea7,0x263e2c72,0xac72a63e,0xaea7afd9,0x2c72263e,0x2ea72fd9,0x263e2c72,0xafd9aea7,0xa63eac72,0x2fd92ea7,0x2ea72fd9,0xac72a63e,0xaea7afd9,0x2c72263e,
0x2da83000,0xada8b000,0x2da83000,0xada8b000,0xada80000,0x2da88000,0xada80000,0x2da88000,0xada88000,0x2da88000,0xada80000,0x2da88000,0xada8b000,0x2da83000,0xada8b000,0x2da83000,
0x2a1f2f64,0xaa1faf64,0x2a1f2f64,0xaa1faf64,0xaf64aa1f,0x2f642a1f,0xaf64aa1f,0x2f642a1f,0xaf64aa1f,0x2f642a1f,0xaf64aa1f,0x2f642a1f,0xaa1faf64,0x2a1f2f64,0xaa1faf64,0x2a1f2f64,
0xaf64ada8,0xaa1f2da8,0x2f642da8,0x2a1fada8,0x2a1f3000,0x2f648000,0xaa1fb000,0xaf640000,0x2a1fada8,0xaf64ada8,0xaa1f2da8,0x2f642da8,0xaf648000,0x2a1f3000,0x2f648000,0xaa1fb000,
0xac72afd9,0xaea7263e,0x2c722fd9,0x2ea7a63e,0xa63e2ea7,0x2fd92c72,0x263eaea7,0xafd9ac72,0x2ea7a63e,0xac72afd9,0xaea7263e,0x2c722fd9,0xafd9ac72,0xa63e2ea7,0x2fd92c72,0x263eaea7,
0xada8ada8,0xada8ada8,0xada8ada8,0xada8ada8,0x2da82da8,0x2da82da8,0x2da82da8,0x2da82da8,0xada82da8,0xada82da8,0xada82da8,0xada82da8,0x2da8ada8,0x2da8ada8,0x2da8ada8,0x2da8ada8,
0xb0008000,0xb0000000,0xb0000000,0xb0000000,0x30008000,0x30008000,0x30008000,0x30008000,0x3000,0x3000,0x3000,0x80003000,0x8000b000,0x8000b000,0x8000b000,0x8000b000,
0xac722fd9,0xaea7a63e,0x2c72afd9,0x2ea7263e,0xa63eaea7,0x2fd9ac72,0x263e2ea7,0xafd92c72,0x2ea7263e,0xac722fd9,0xaea7a63e,0x2c72afd9,0xafd92c72,0xa63eaea7,0x2fd9ac72,0x263e2ea7,
0x2a1f2da8,0xaf642da8,0xaa1fada8,0x2f64ada8,0xaf648000,0x2a1fb000,0x2f648000,0xaa1f3000,0x2f64ada8,0x2a1f2da8,0xaf642da8,0xaa1fada8,0xaa1f3000,0xaf640000,0x2a1fb000,0x2f648000,
0xaf642a1f,0x2f64aa1f,0xaf642a1f,0x2f64aa1f,0xaa1f2f64,0x2a1faf64,0xaa1f2f64,0x2a1faf64,0x2a1faf64,0xaa1f2f64,0x2a1faf64,0xaa1f2f64,0xaf642a1f,0x2f64aa1f,0xaf642a1f,0x2f64aa1f,
0xada83000,0x2da8b000,0xada83000,0x2da8b000,0x2da88000,0xada80000,0x2da88000,0xada88000,0xada88000,0x2da88000,0xada80000,0x2da88000,0xada83000,0x2da8b000,0xada83000,0x2da8b000,
0xafd92ea7,0xa63e2c72,0x2fd9aea7,0x263eac72,0xac72263e,0xaea72fd9,0x2c72a63e,0x2ea7afd9,0x263eac72,0xafd92ea7,0xa63e2c72,0x2fd9aea7,0x2ea7afd9,0xac72263e,0xaea72fd9,0x2c72a63e,
0xaa1f2da8,0x2f64ada8,0x2a1fada8,0xaf642da8,0xaf643000,0x2a1f8000,0x2f64b000,0xaa1f8000,0xaf642da8,0xaa1f2da8,0x2f64ada8,0x2a1fada8,0xaa1f8000,0xaf643000,0x2a1f8000,0x2f64b000,
0x80008000,0x80000000,0x80000000,0x0,0x80000000,0x80000000,0x80000000,0x80000000,0xb0003000,0xb0003000,0xb0003000,0xb0003000,0xb0003000,0xb0003000,0xb0003000,0xb0003000,
0x3000b000,0x3000b000,0x3000b000,0x3000b000,0x3000b000,0x3000b000,0x3000b000,0x3000b000,0x80000000,0x80000000,0x80008000,0x80008000,0x80000000,0x80008000,0x80008000,0x80008000,
0x2f64ada8,0x2a1fada8,0xaf642da8,0xaa1f2da8,0x2a1f8000,0x2f64b000,0xaa1f8000,0xaf643000,0xaa1f2da8,0x2f64ada8,0x2a1fada8,0xaf642da8,0xaf643000,0x2a1f0000,0x2f64b000,0xaa1f8000,
0x263eac72,0xafd92ea7,0xa63e2c72,0x2fd9aea7,0x2ea7afd9,0xac72263e,0xaea72fd9,0x2c72a63e,0x2fd9aea7,0x263eac72,0xafd92ea7,0xa63e2c72,0x2c72a63e,0x2ea7afd9,0xac72263e,0xaea72fd9,
0xada83000,0x2da8b000,0xada83000,0x2da8b000,0x2da80000,0xada88000,0x2da88000,0xada88000,0x2da88000,0xada88000,0x2da80000,0xada88000,0x2da8b000,0xada83000,0x2da8b000,0xada83000,
0x2f64aa1f,0xaf642a1f,0x2f64aa1f,0xaf642a1f,0x2a1faf64,0xaa1f2f64,0x2a1faf64,0xaa1f2f64,0x2a1faf64,0xaa1f2f64,0x2a1faf64,0xaa1f2f64,0xaf642a1f,0x2f64aa1f,0xaf642a1f,0x2f64aa1f,
0x2f64ada8,0x2a1f2da8,0xaf642da8,0xaa1fada8,0xaa1f3000,0xaf648000,0x2a1fb000,0x2f640000,0xaa1fada8,0x2f64ada8,0x2a1f2da8,0xaf642da8,0x2f648000,0xaa1f3000,0xaf648000,0x2a1fb000,
0xaea7a63e,0x2c72afd9,0x2ea7263e,0xac722fd9,0x2fd9ac72,0x263e2ea7,0xafd92c72,0xa63eaea7,0xac722fd9,0xaea7a63e,0x2c72afd9,0x2ea7263e,0xa63eaea7,0x2fd9ac72,0x263e2ea7,0xafd92c72,
0xada8ada8,0xada8ada8,0xada8ada8,0xada8ada8,0x2da82da8,0x2da82da8,0x2da82da8,0x2da82da8,0x2da8ada8,0x2da8ada8,0x2da8ada8,0x2da8ada8,0xada82da8,0xada82da8,0xada82da8,0xada82da8,
0x30008000,0x30000000,0x30000000,0x30000000,0xb0008000,0xb0008000,0xb0008000,0xb0000000,0x80003000,0x80003000,0x80003000,0x3000,0xb000,0x8000b000,0xb000,0xb000,
0x2ea7a63e,0xac72afd9,0xaea7263e,0x2c722fd9,0xafd9ac72,0xa63e2ea7,0x2fd92c72,0x263eaea7,0x2c722fd9,0x2ea7a63e,0xac72afd9,0xaea7263e,0x263eaea7,0xafd9ac72,0xa63e2ea7,0x2fd92c72,
0xaa1f2da8,0x2f642da8,0x2a1fada8,0xaf64ada8,0x2f648000,0xaa1fb000,0xaf640000,0x2a1f3000,0xaf64ada8,0xaa1f2da8,0x2f642da8,0x2a1fada8,0x2a1f3000,0x2f648000,0xaa1fb000,0xaf648000,
0xaa1faf64,0x2a1f2f64,0xaa1faf64,0x2a1f2f64,0x2f642a1f,0xaf64aa1f,0x2f642a1f,0xaf64aa1f,0xaf64aa1f,0x2f642a1f,0xaf64aa1f,0x2f642a1f,0xaa1faf64,0x2a1f2f64,0xaa1faf64,0x2a1f2f64,
0x2da83000,0xada8b000,0x2da83000,0xada8b000,0xada88000,0x2da88000,0xada88000,0x2da80000,0x2da88000,0xada88000,0x2da80000,0xada80000,0x2da83000,0xada8b000,0x2da83000,0xada8b000,
0xa63eac72,0x2fd92ea7,0x263e2c72,0xafd9aea7,0xaea7afd9,0x2c72263e,0x2ea72fd9,0xac72a63e,0xafd9aea7,0xa63eac72,0x2fd92ea7,0x263e2c72,0xac72a63e,0xaea7afd9,0x2c72263e,0x2ea72fd9,
0x2a1f2da8,0xaf64ada8,0xaa1fada8,0x2f642da8,0x2f643000,0xaa1f8000,0xaf64b000,0x2a1f0000,0x2f642da8,0x2a1f2da8,0xaf64ada8,0xaa1fada8,0x2a1f8000,0x2f643000,0xaa1f8000,0xaf64b000,
0x3c003c00,0x3c003c00,0x3c003c00,0x3c003c00,0x3c003c00,0x3c003c00,0x3c003c00,0x3c003c00,0x80008000,0x80008000,0x80008000,0x80008000,0x80008000,0x80008000,0x80008000,0x80008000,
0x3bd93c00,0x3aa73b64,0x387239a8,0x323e361f,0xb23e0000,0xb872b61f,0xbaa7b9a8,0xbbd9bb64,0xb23e8000,0xb872b61f,0xbaa7b9a8,0xbbd9bb64,0xbbd9bc00,0xbaa7bb64,0xb872b9a8,0xb23eb61f,
0xbb64bc00,0xb61fb9a8,0x361f8000,0x3b6439a8,0x3b643c00,0x361f39a8,0xb61f0000,0xbb64b9a8,0x361f8000,0x3b6439a8,0x3b643c00,0x361f39a8,0xb61f8000,0xbb64b9a8,0xbb64bc00,0xb61fb9a8,
0x38728000,0x3bd93b64,0x323e39a8,0xbaa7b61f,0x3aa73c00,0xb23e361f,0xbbd9b9a8,0xb872bb64,0x3aa73c00,0xb23e361f,0xbbd9b9a8,0xb872bb64,0xb8728000,0xbbd9bb64,0xb23eb9a8,0x3aa7361f,
0xbc008000,0x3c008000,0xbc000000,0x3c008000,0xbc000000,0x3c008000,0xbc000000,0x3c008000,0x3c00,0x8000bc00,0x3c00,0x8000bc00,0x3c00,0x8000bc00,0x80003c00,0x8000bc00,
0xbbd98000,0x3aa7361f,0xb872b9a8,0x323e3b64,0x323ebc00,0xb8723b64,0x3aa7b9a8,0xbbd9361f,0xb23e3c00,0x3872bb64,0xbaa739a8,0x3bd9b61f,0xbbd90000,0x3aa7361f,0xb872b9a8,0x323e3b64,
0x3b648000,0xb61fb9a8,0xb61f3c00,0x3b64b9a8,0xbb648000,0x361f39a8,0x361fbc00,0xbb6439a8,0x361fbc00,0xbb6439a8,0x3b648000,0xb61fb9a8,0xb61f3c00,0x3b64b9a8,0xbb640000,0x361f39a8,
0xb8723c00,0x3bd9b61f,0xb23eb9a8,0xbaa73b64,0xbaa78000,0xb23e3b64,0x3bd9b9a8,0xb872b61f,0x3aa78000,0x323ebb64,0xbbd939a8,0x3872361f,0xb8723c00,0x3bd9b61f,0xb23eb9a8,0xbaa73b64,
0xbbd93c00,0xbaa73b64,0xb87239a8,0xb23e361f,0x323e8000,0x3872b61f,0x3aa7b9a8,0x3bd9bb64,0x323e8000,0x3872b61f,0x3aa7b9a8,0x3bd9bb64,0x3bd9bc00,0x3aa7bb64,0x3872b9a8,0x323eb61f,
0xbc003c00,0xbc003c00,0xbc003c00,0xbc003c00,0xbc003c00,0xbc003c00,0xbc003c00,0xbc003c00,0x80008000,0x80000000,0x80000000,0x80000000,0x80000000,0x80000000,0x0,0x80000000,
0xb8728000,0xbbd93b64,0xb23e39a8,0x3aa7b61f,0xbaa73c00,0x323e361f,0x3bd9b9a8,0x3872bb64,0xbaa73c00,0x323e361f,0x3bd9b9a8,0x3872bb64,0x38728000,0x3bd9bb64,0x323eb9a8,0xbaa7361f,
0x3b64bc00,0x361fb9a8,0xb61f8000,0xbb6439a8,0xbb643c00,0xb61f39a8,0x361f0000,0x3b64b9a8,0xb61f8000,0xbb6439a8,0xbb643c00,0xb61f39a8,0x361f8000,0x3b64b9a8,0x3b64bc00,0x361fb9a8,
0x3bd98000,0xbaa7361f,0x3872b9a8,0xb23e3b64,0xb23ebc00,0x38723b64,0xbaa7b9a8,0x3bd9361f,0x323e3c00,0xb872bb64,0x3aa739a8,0xbbd9b61f,0x3bd98000,0xbaa7361f,0x3872b9a8,0xb23e3b64,
0x3c008000,0xbc008000,0x3c000000,0xbc008000,0x3c000000,0xbc008000,0x3c000000,0xbc000000,0x80003c00,0xbc00,0x80003c00,0x8000bc00,0x80003c00,0xbc00,0x80003c00,0xbc00,
0x38723c00,0xbbd9b61f,0x323eb9a8,0x3aa73b64,0x3aa78000,0x323e3b64,0xbbd9b9a8,0x3872b61f,0xbaa78000,0xb23ebb64,0x3bd939a8,0xb872361f,0x38723c00,0xbbd9b61f,0x323eb9a8,0x3aa73b64,
0xbb640000,0x361fb9a8,0x361f3c00,0xbb64b9a8,0x3b648000,0xb61f39a8,0xb61fbc00,0x3b6439a8,0xb61fbc00,0x3b6439a8,0xbb640000,0x361fb9a8,0x361f3c00,0xbb64b9a8,0x3b648000,0xb61f39a8,
0x39a83c00,0xb9a80000,0xb9a8bc00,0x39a88000,0x39a83c00,0xb9a80000,0xb9a8bc00,0x39a88000,0xb9a88000,0xb9a8bc00,0x39a88000,0x39a83c00,0xb9a80000,0xb9a8bc00,0x39a88000,0x39a83c00,
0x38723c00,0xbbd9b61f,0x323eb9a8,0x3aa73b64,0xbaa70000,0xb23ebb64,0x3bd939a8,0xb872361f,0xbaa78000,0xb23ebb64,0x3bd939a8,0xb872361f,0xb872bc00,0x3bd9361f,0xb23e39a8,0xbaa7bb64,
0xb61fbc00,0x3b6439a8,0xbb640000,0x361fb9a8,0x361f3c00,0xbb64b9a8,0x3b648000,0xb61f39a8,0x3b648000,0xb61f39a8,0xb61fbc00,0x3b6439a8,0xbb648000,0x361fb9a8,0x361f3c00,0xbb64b9a8,
0x3bd98000,0xbaa7361f,0x3872b9a8,0xb23e3b64,0x323e3c00,0xb872bb64,0x3aa739a8,0xbbd9b61f,0x323e3c00,0xb872bb64,0x3aa739a8,0xbbd9b61f,0xbbd98000,0x3aa7b61f,0xb87239a8,0x323ebb64,
0xb9a88000,0xb9a83c00,0x39a88000,0x39a8bc00,0xb9a80000,0xb9a83c00,0x39a88000,0x39a8bc00,0xb9a83c00,0x39a88000,0x39a8bc00,0xb9a80000,0xb9a83c00,0x39a88000,0x39a8bc00,0xb9a88000,
0xb8728000,0xbbd93b64,0xb23e39a8,0x3aa7b61f,0x3aa7bc00,0xb23eb61f,0xbbd939a8,0xb8723b64,0xbaa73c00,0x323e361f,0x3bd9b9a8,0x3872bb64,0xb8728000,0xbbd93b64,0xb23e39a8,0x3aa7b61f,
0x361f8000,0x3b64b9a8,0x3b64bc00,0x361fb9a8,0xb61f8000,0xbb6439a8,0xbb643c00,0xb61f39a8,0x3b64bc00,0x361fb9a8,0xb61f8000,0xbb6439a8,0xbb643c00,0xb61f39a8,0x361f8000,0x3b64b9a8,
0xbbd93c00,0xbaa73b64,0xb87239a8,0xb23e361f,0xb23e8000,0xb872361f,0xbaa739a8,0xbbd93b64,0x323e8000,0x3872b61f,0x3aa7b9a8,0x3bd9bb64,0xbbd93c00,0xbaa73b64,0xb87239a8,0xb23e361f,
0xb8723c00,0x3bd9b61f,0xb23eb9a8,0xbaa73b64,0x3aa78000,0x323ebb64,0xbbd939a8,0x3872361f,0x3aa78000,0x323ebb64,0xbbd939a8,0x3872361f,0x3872bc00,0xbbd9361f,0x323e39a8,0x3aa7bb64,
0xb9a83c00,0x39a80000,0x39a8bc00,0xb9a88000,0xb9a83c00,0x39a88000,0x39a8bc00,0xb9a88000,0x39a88000,0x39a8bc00,0xb9a88000,0xb9a83c00,0x39a80000,0x39a8bc00,0xb9a88000,0xb9a83c00,
0xbbd98000,0x3aa7361f,0xb872b9a8,0x323e3b64,0xb23e3c00,0x3872bb64,0xbaa739a8,0x3bd9b61f,0xb23e3c00,0x3872bb64,0xbaa739a8,0x3bd9b61f,0x3bd98000,0xbaa7b61f,0x387239a8,0xb23ebb64,
0x361fbc00,0xbb6439a8,0x3b640000,0xb61fb9a8,0xb61f3c00,0x3b64b9a8,0xbb648000,0x361f39a8,0xbb648000,0x361f39a8,0x361fbc00,0xbb6439a8,0x3b648000,0xb61fb9a8,0xb61f3c00,0x3b64b9a8,
0x38728000,0x3bd93b64,0x323e39a8,0xbaa7b61f,0xbaa7bc00,0x323eb61f,0x3bd939a8,0x38723b64,0x3aa73c00,0xb23e361f,0xbbd9b9a8,0xb872bb64,0x38728000,0x3bd93b64,0x323e39a8,0xbaa7b61f,
0x39a88000,0x39a83c00,0xb9a88000,0xb9a8bc00,0x39a80000,0x39a83c00,0xb9a80000,0xb9a8bc00,0x39a83c00,0xb9a88000,0xb9a8bc00,0x39a88000,0x39a83c00,0xb9a88000,0xb9a8bc00,0x39a80000,
0x3bd93c00,0x3aa73b64,0x387239a8,0x323e361f,0x323e8000,0x3872361f,0x3aa739a8,0x3bd93b64,0xb23e8000,0xb872b61f,0xbaa7b9a8,0xbbd9bb64,0x3bd93c00,0x3aa73b64,0x387239a8,0x323e361f,
0xb61f8000,0xbb64b9a8,0xbb64bc00,0xb61fb9a8,0x361f8000,0x3b6439a8,0x3b643c00,0x361f39a8,0xbb64bc00,0xb61fb9a8,0x361f0000,0x3b6439a8,0x3b643c00,0x361f39a8,0xb61f8000,0xbb64b9a8,
0x0,0x0,0x0,0x0,0x0,0x0,0x0,0x0,0x3c003c00,0x3c003c00,0x3c003c00,0x3c003c00,0x3c003c00,0x3c003c00,0x3c003c00,0x3c003c00,
0x323e0000,0x3872361f,0x3aa739a8,0x3bd93b64,0x3bd93c00,0x3aa73b64,0x387239a8,0x323e361f,0x3bd93c00,0x3aa73b64,0x387239a8,0x323e361f,0xb23e0000,0xb872b61f,0xbaa7b9a8,0xbbd9bb64,
0xb61f0000,0xbb64b9a8,0xbb64bc00,0xb61fb9a8,0x361f0000,0x3b6439a8,0x3b643c00,0x361f39a8,0xbb64bc00,0xb61fb9a8,0x361f8000,0x3b6439a8,0x3b643c00,0x361f39a8,0xb61f0000,0xbb64b9a8,
0xbaa7bc00,0x323eb61f,0x3bd939a8,0x38723b64,0x38720000,0x3bd93b64,0x323e39a8,0xbaa7b61f,0x38728000,0x3bd93b64,0x323e39a8,0xbaa7b61f,0x3aa73c00,0xb23e361f,0xbbd9b9a8,0xb872bb64,
0x3c00,0x8000bc00,0x3c00,0x8000bc00,0x3c00,0x8000bc00,0x80003c00,0x8000bc00,0x3c000000,0xbc000000,0x3c008000,0xbc000000,0x3c008000,0xbc000000,0x3c008000,0xbc000000,
0xb23e3c00,0x3872bb64,0xbaa739a8,0x3bd9b61f,0xbbd90000,0x3aa7361f,0xb872b9a8,0x323e3b64,0x3bd90000,0xbaa7b61f,0x387239a8,0xb23ebb64,0xb23e3c00,0x3872bb64,0xbaa739a8,0x3bd9b61f,
0x361fbc00,0xbb6439a8,0x3b648000,0xb61fb9a8,0xb61f3c00,0x3b64b9a8,0xbb640000,0x361f39a8,0xbb640000,0x361f39a8,0x361fbc00,0xbb6439a8,0x3b640000,0xb61fb9a8,0xb61f3c00,0x3b64b9a8,
0x3aa78000,0x323ebb64,0xbbd939a8,0x3872361f,0xb8723c00,0x3bd9b61f,0xb23eb9a8,0xbaa73b64,0x3872bc00,0xbbd9361f,0x323e39a8,0x3aa7bb64,0x3aa70000,0x323ebb64,0xbbd939a8,0x3872361f,
0xb23e0000,0xb872361f,0xbaa739a8,0xbbd93b64,0xbbd93c00,0xbaa73b64,0xb87239a8,0xb23e361f,0xbbd93c00,0xbaa73b64,0xb87239a8,0xb23e361f,0x323e8000,0x3872b61f,0x3aa7b9a8,0x3bd9bb64,
0x0,0x8000,0x8000,0x8000,0x8000,0x8000,0x80008000,0x8000,0xbc003c00,0xbc003c00,0xbc003c00,0xbc003c00,0xbc003c00,0xbc003c00,0xbc003c00,0xbc003c00,
0x3aa7bc00,0xb23eb61f,0xbbd939a8,0xb8723b64,0xb8720000,0xbbd93b64,0xb23e39a8,0x3aa7b61f,0xb8728000,0xbbd93b64,0xb23e39a8,0x3aa7b61f,0xbaa73c00,0x323e361f,0x3bd9b9a8,0x3872bb64,
0x361f0000,0x3b64b9a8,0x3b64bc00,0x361fb9a8,0xb61f0000,0xbb6439a8,0xbb643c00,0xb61f39a8,0x3b64bc00,0x361fb9a8,0xb61f8000,0xbb6439a8,0xbb643c00,0xb61f39a8,0x361f0000,0x3b64b9a8,
0x323e3c00,0xb872bb64,0x3aa739a8,0xbbd9b61f,0x3bd98000,0xbaa7361f,0x3872b9a8,0xb23e3b64,0xbbd90000,0x3aa7b61f,0xb87239a8,0x323ebb64,0x323e3c00,0xb872bb64,0x3aa739a8,0xbbd9b61f,
0x80003c00,0xbc00,0x80003c00,0x8000bc00,0x80003c00,0xbc00,0x80003c00,0xbc00,0xbc000000,0x3c000000,0xbc008000,0x3c000000,0xbc008000,0x3c000000,0xbc008000,0x3c008000,
0xbaa78000,0xb23ebb64,0x3bd939a8,0xb872361f,0x38723c00,0xbbd9b61f,0x323eb9a8,0x3aa73b64,0xb872bc00,0x3bd9361f,0xb23e39a8,0xbaa7bb64,0xbaa70000,0xb23ebb64,0x3bd939a8,0xb872361f,
0xb61fbc00,0x3b6439a8,0xbb640000,0x361fb9a8,0x361f3c00,0xbb64b9a8,0x3b648000,0xb61f39a8,0x3b648000,0xb61f39a8,0xb61fbc00,0x3b6439a8,0xbb640000,0x361fb9a8,0x361f3c00,0xbb64b9a8,
0x39a80000,0x39a83c00,0xb9a80000,0xb9a8bc00,0x39a88000,0x39a83c00,0xb9a80000,0xb9a8bc00,0x39a83c00,0xb9a80000,0xb9a8bc00,0x39a88000,0x39a83c00,0xb9a80000,0xb9a8bc00,0x39a88000,
0x3aa70000,0x323e3b64,0xbbd9b9a8,0x3872b61f,0x38723c00,0xbbd9b61f,0x323eb9a8,0x3aa73b64,0x38723c00,0xbbd9b61f,0x323eb9a8,0x3aa73b64,0xbaa70000,0xb23ebb64,0x3bd939a8,0xb872361f,
0xbb640000,0x361fb9a8,0x361f3c00,0xbb64b9a8,0x3b640000,0xb61f39a8,0xb61fbc00,0x3b6439a8,0xb61fbc00,0x3b6439a8,0xbb640000,0x361fb9a8,0x361f3c00,0xbb64b9a8,0x3b648000,0xb61f39a8,
0xb23ebc00,0x38723b64,0xbaa7b9a8,0x3bd9361f,0x3bd90000,0xbaa7361f,0x3872b9a8,0xb23e3b64,0x3bd98000,0xbaa7361f,0x3872b9a8,0xb23e3b64,0x323e3c00,0xb872bb64,0x3aa739a8,0xbbd9b61f,
0xb9a83c00,0x39a88000,0x39a8bc00,0xb9a80000,0xb9a83c00,0x39a88000,0x39a8bc00,0xb9a88000,0x39a80000,0x39a8bc00,0xb9a80000,0xb9a83c00,0x39a88000,0x39a8bc00,0xb9a80000,0xb9a83c00,
0xbaa73c00,0x323e361f,0x3bd9b9a8,0x3872bb64,0xb8728000,0xbbd93b64,0xb23e39a8,0x3aa7b61f,0x38720000,0x3bd9bb64,0x323eb9a8,0xbaa7361f,0xbaa73c00,0x323e361f,0x3bd9b9a8,0x3872bb64,
0x3b64bc00,0x361fb9a8,0xb61f8000,0xbb6439a8,0xbb643c00,0xb61f39a8,0x361f8000,0x3b64b9a8,0xb61f0000,0xbb6439a8,0xbb643c00,0xb61f39a8,0x361f0000,0x3b64b9a8,0x3b64bc00,0x361fb9a8,
0x323e8000,0x3872b61f,0x3aa7b9a8,0x3bd9bb64,0xbbd93c00,0xbaa73b64,0xb87239a8,0xb23e361f,0x3bd9bc00,0x3aa7bb64,0x3872b9a8,0x323eb61f,0x323e0000,0x3872b61f,0x3aa7b9a8,0x3bd9bb64,
0xbaa70000,0xb23e3b64,0x3bd9b9a8,0xb872b61f,0xb8723c00,0x3bd9b61f,0xb23eb9a8,0xbaa73b64,0xb8723c00,0x3bd9b61f,0xb23eb9a8,0xbaa73b64,0x3aa78000,0x323ebb64,0xbbd939a8,0x3872361f,
0xb9a80000,0xb9a83c00,0x39a80000,0x39a8bc00,0xb9a88000,0xb9a83c00,0x39a80000,0x39a8bc00,0xb9a83c00,0x39a80000,0x39a8bc00,0xb9a88000,0xb9a83c00,0x39a88000,0x39a8bc00,0xb9a88000,
0x323ebc00,0xb8723b64,0x3aa7b9a8,0xbbd9361f,0xbbd90000,0x3aa7361f,0xb872b9a8,0x323e3b64,0xbbd98000,0x3aa7361f,0xb872b9a8,0x323e3b64,0xb23e3c00,0x3872bb64,0xbaa739a8,0x3bd9b61f,
0x3b640000,0xb61fb9a8,0xb61f3c00,0x3b64b9a8,0xbb640000,0x361f39a8,0x361fbc00,0xbb6439a8,0x361fbc00,0xbb6439a8,0x3b640000,0xb61fb9a8,0xb61f3c00,0x3b64b9a8,0xbb648000,0x361f39a8,
0x3aa73c00,0xb23e361f,0xbbd9b9a8,0xb872bb64,0x38728000,0x3bd93b64,0x323e39a8,0xbaa7b61f,0xb8720000,0xbbd9bb64,0xb23eb9a8,0x3aa7361f,0x3aa73c00,0xb23e361f,0xbbd9b9a8,0xb872bb64,
0x39a83c00,0xb9a88000,0xb9a8bc00,0x39a88000,0x39a83c00,0xb9a88000,0xb9a8bc00,0x39a80000,0xb9a80000,0xb9a8bc00,0x39a80000,0x39a83c00,0xb9a88000,0xb9a8bc00,0x39a88000,0x39a83c00,
0xb23e8000,0xb872b61f,0xbaa7b9a8,0xbbd9bb64,0x3bd93c00,0x3aa73b64,0x387239a8,0x323e361f,0xbbd9bc00,0xbaa7bb64,0xb872b9a8,0xb23eb61f,0xb23e0000,0xb872b61f,0xbaa7b9a8,0xbbd9bb64,
0xbb64bc00,0xb61fb9a8,0x361f0000,0x3b6439a8,0x3b643c00,0x361f39a8,0xb61f8000,0xbb64b9a8,0x361f0000,0x3b6439a8,0x3b643c00,0x361f39a8,0xb61f0000,0xbb64b9a8,0xbb64bc00,0xb61fb9a8,
};
__device__ __align__(1024) bf16 g_x1T[DM * XP];
__device__ __align__(1024) bf16 g_x2T[2][DM * XP];
__device__ __align__(1024) float g_fs[2][SEQ];

#define TS_SMEM 0
#define TS_DECL
#define TS_ARG
#define TS_PASS
#define TS_PHASE(p)
#define TS(i)
#define TSX(row, i)
#define TS_BEGIN
#define TS_END

struct cplx { float r, i; };
__device__ __forceinline__ cplx cmul(cplx a, cplx b) {
    cplx o;
    o.r = fmaf(a.r, b.r, -a.i * b.i);
    o.i = fmaf(a.r, b.i, a.i * b.r);
    return o;
}
__device__ __forceinline__ cplx csq(cplx a) {
    cplx o;
    o.r = fmaf(a.r, a.r, -a.i * a.i);
    o.i = 2.f * a.r * a.i;
    return o;
}
__device__ __forceinline__ cplx cexp_p(float arl, float ai, float p) {
    float mag = ex2(arl * p);
    float ang = ai * p;
    float n = rintf(ang * 0.15915494309189535f);
    float r = fmaf(n, -6.2831854820251465f, ang);
    r = fmaf(n, 1.7484555e-7f, r);
    cplx o;
    o.r = mag * __cosf(r);
    o.i = mag * __sinf(r);
    return o;
}

__device__ __forceinline__ uint32_t pack2h(float lo, float hi) {
    uint32_t r;
    asm("cvt.rn.f16x2.f32 %0, %1, %2;" : "=r"(r) : "f"(hi), "f"(lo));
    return r;
}
__device__ __forceinline__ uint32_t hmul(uint32_t a, uint32_t b) { uint32_t d; asm("mul.rn.f16x2 %0, %1, %2;" : "=r"(d) : "r"(a), "r"(b)); return d; }
__device__ __forceinline__ uint32_t hfma(uint32_t a, uint32_t b, uint32_t c) { uint32_t d; asm("fma.rn.f16x2 %0, %1, %2, %3;" : "=r"(d) : "r"(a), "r"(b), "r"(c)); return d; }
__device__ __forceinline__ uint32_t hfms(uint32_t a, uint32_t b, uint32_t c) {
    uint32_t d;
    asm("{\n.reg .b32 n;\nneg.f16x2 n, %1;\nfma.rn.f16x2 %0, n, %2, %3;\n}" : "=r"(d) : "r"(a), "r"(b), "r"(c));
    return d;
}
__device__ __forceinline__ uint32_t hadd(uint32_t a, uint32_t b) { uint32_t d; asm("add.rn.f16x2 %0, %1, %2;" : "=r"(d) : "r"(a), "r"(b)); return d; }
__device__ __forceinline__ uint32_t hsub(uint32_t a, uint32_t b) { uint32_t d; asm("sub.rn.f16x2 %0, %1, %2;" : "=r"(d) : "r"(a), "r"(b)); return d; }
__device__ __forceinline__ uint4 ldg_tab(int tab, int t) { return ldg128((const uint4*)c_fft + t + tab * 128); }
__device__ __forceinline__ uint32_t u4(const uint4& v, int i) { return i == 0 ? v.x : i == 1 ? v.y : i == 2 ? v.z : v.w; }
struct cpair { uint32_t r, i; };
__device__ __forceinline__ cpair pmul(cpair p, uint32_t z) {
    const __half2 zv = *reinterpret_cast<const __half2*>(&z), pr = *reinterpret_cast<const __half2*>(&p.r), pi = *reinterpret_cast<const __half2*>(&p.i);
    const __half2 zr = __low2half2(zv), zi = __high2half2(zv);
    const __half2 a = __hfma2(__hneg2(pi), zi, __hmul2(pr, zr)), b = __hfma2(pi, zr, __hmul2(pr, zi));
    return {*reinterpret_cast<const uint32_t*>(&a), *reinterpret_cast<const uint32_t*>(&b)};
}
__device__ __forceinline__ uint32_t packz(cplx z) { return pack2h(z.r, z.i); }
__device__ __forceinline__ void wgmma_kg(float (&d)[24], uint64_t da, uint64_t db, int scale_d) {
    asm volatile("{\n.reg .pred p;\nsetp.ne.b32 p, %26, 0;\n"
                 "wgmma.mma_async.sync.aligned.m64n48k16.f32.f16.f16 "
                 "{%0,%1,%2,%3,%4,%5,%6,%7,%8,%9,%10,%11,%12,%13,%14,%15,%16,%17,%18,%19,%20,%21,%22,%23}, %24, %25, p, 1, 1, 1, 1;\n}\n"
                 : "+f"(d[0]), "+f"(d[1]), "+f"(d[2]), "+f"(d[3]), "+f"(d[4]), "+f"(d[5]), "+f"(d[6]), "+f"(d[7]), "+f"(d[8]), "+f"(d[9]),
                   "+f"(d[10]), "+f"(d[11]), "+f"(d[12]), "+f"(d[13]), "+f"(d[14]), "+f"(d[15]), "+f"(d[16]), "+f"(d[17]), "+f"(d[18]), "+f"(d[19]),
                   "+f"(d[20]), "+f"(d[21]), "+f"(d[22]), "+f"(d[23])
                 : "l"(da), "l"(db), "r"(scale_d));
}

struct SsmParams { const bf16 *lar, *aim, *cre, *cim, *logdt, *dskip; };
constexpr int KG_TABLES = 6 * 16384, KG_RES = 1664;
struct KgShared { uint32_t kmax[6], kexp[6]; float cinv[6]; };
struct KgParams { uint32_t l[3], a[3], r[3], i[3], dt, ds; };

__device__ __forceinline__ bool kg_is_hi(int warp) { return ((warp >> 1) ^ (warp >> 2)) & 1; }
__device__ __forceinline__ void kgen_load(KgParams& kp, int d0, int warp, int lane, const SsmParams& sp) {
    const int d = d0 + min(2 * (warp >> 2) + (warp & 1), 4), idx = d * (NMODE / 2) + lane;
    const bf16 *pr = kg_is_hi(warp) ? sp.cre : sp.lar, *pi = kg_is_hi(warp) ? sp.cim : sp.aim;
    kp.dt = __ldg((const uint16_t*)sp.logdt + d);
#pragma unroll
    for (int j = 0; j < 3; j++) {
        kp.l[j] = __ldg((const uint32_t*)sp.lar + idx + 32 * j); kp.a[j] = __ldg((const uint32_t*)sp.aim + idx + 32 * j);
        kp.r[j] = __ldg((const uint32_t*)pr + idx + 32 * j); kp.i[j] = __ldg((const uint32_t*)pi + idx + 32 * j);
    }
    kp.ds = __ldg((const uint16_t*)sp.dskip + d0 + min(warp >> 1, 4));
}

struct KgAnchors { uint32_t v[8]; };
__device__ __forceinline__ KgAnchors kg_anchor_lo(const KgParams& kp, uint32_t sel, float dt) {
    auto B = [&](uint32_t v) { return __uint_as_float(__byte_perm(v, 0u, sel)); };
    const float arl = -rbf(ex2(B(kp.l[0]) * 1.4426950408889634f)) * dt * 1.4426950408889634f, ai = B(kp.a[0]) * dt;
    const cplx z8 = cexp_p(arl, ai, 8.f), z16 = csq(z8), z24 = cmul(z16, z8), z32 = csq(z16), z64 = csq(z32), z128 = csq(z64), z192 = cmul(z128, z64);
    return {{pack2h(1.f, z8.r), pack2h(0.f, z8.i), pack2h(z16.r, z24.r), pack2h(z16.i, z24.i), packz(z32), packz(z64), packz(z128), packz(z192)}};
}
__device__ __forceinline__ KgAnchors kg_anchor_hi(const KgParams& kp, uint32_t sel, float dt, float cs) {
    auto B = [&](uint32_t v) { return __uint_as_float(__byte_perm(v, 0u, sel)); };
    const float arl = -rbf(ex2(B(kp.l[0]) * 1.4426950408889634f)) * dt * 1.4426950408889634f, ai = B(kp.a[0]) * dt;
    const cplx z1 = cexp_p(arl, -ai, 1.f), z2 = csq(z1), z4 = csq(z2), z256 = cexp_p(arl, -ai, 256.f), z512 = csq(z256), z1024 = csq(z512);
    const cplx H0 = {B(kp.r[0]) * cs, -B(kp.i[0]) * cs}, H4 = cmul(H0, z4);
    return {{pack2h(H0.r, H4.r), pack2h(H0.i, H4.i), packz(z1), packz(z2), packz(z256), packz(z512), packz(z1024), 0u}};
}

__device__ __forceinline__ void kgen_tables(KgParams& kp, uint32_t scr, uint32_t dump, KgShared* ks, int warp, int lane TS_ARG) {
    const int wg = warp >> 2, half = warp & 1, sw = lane & 7;
    const bool hi = kg_is_hi(warp);
    TS(23);
    const float dt = rbf(ex2(bf_lo(kp.dt) * 1.4426950408889634f));
    uint32_t sel = (wg == 2 && half) ? 0x3244u : 0x1044u;
    float cs = 0.f;
    KgAnchors an;
    if (hi) {
        uint32_t m = 0;
#pragma unroll
        for (int j = 0; j < 3; j++) m = __vmaxu2(m, __vmaxu2(kp.r[j] & 0x7FFF7FFFu, kp.i[j] & 0x7FFF7FFFu));
        m = __reduce_max_sync(~0u, max(m << 16, m & 0xFFFF0000u));
        const uint32_t e = min(max(__float_as_uint(2.f * dt * __uint_as_float(m)) >> 23, 2u), 252u);
        cs = 2.f * dt * __uint_as_float((253u - e) << 23);
        if (lane == 0) { ks->cinv[2 * wg + half] = __uint_as_float((e + 1u) << 23); ks->kmax[2 * wg + half] = 0u; }
        an = kg_anchor_hi(kp, sel, dt, cs);
    } else {
        an = kg_anchor_lo(kp, sel, dt);
    }
    float acc[24];
#pragma unroll
    for (int i = 0; i < 24; i++) acc[i] = 0.f;
    uint32_t tb = scr + 2 * wg * 16384 + lane * 128;
    uint64_t da = mkdesc(scr + 2 * wg * 16384, 4096, 1024, 1);
    int flip = 16384;
#pragma unroll 1
    for (int c = wg == 2 ? 1 : 0, step = wg == 2 ? 2 : 1; c < 6; c += step) {
        if (wg < 2) sel ^= 0x2200u;
        if (!hi) {
            if (c & 1) { kp.l[0] = kp.l[1]; kp.l[1] = kp.l[2]; kp.a[0] = kp.a[1]; kp.a[1] = kp.a[2]; }
            cpair p[4];
            p[0] = {an.v[0], an.v[1]}; p[1] = {an.v[2], an.v[3]};
            p[2] = pmul(p[0], an.v[4]); p[3] = pmul(p[1], an.v[4]);
#pragma unroll
            for (int j = 0; j < 4; j++) {
                cpair v[4];
#pragma unroll
                for (int i = 0; i < 4; i++) v[i] = j ? pmul(p[i], an.v[4 + j]) : p[i];
                const uint32_t a = tb + (((4 * half + j) ^ sw) << 4);
                sts128(a, make_uint4(v[0].r, v[1].r, v[2].r, v[3].r));
                sts128(a + 4096, make_uint4(v[0].i, v[1].i, v[2].i, v[3].i));
            }
            an = kg_anchor_lo(kp, sel, dt);
        } else {
            if (c & 1) {
#pragma unroll
                for (int j = 0; j < 2; j++) { kp.l[j] = kp.l[j + 1]; kp.a[j] = kp.a[j + 1]; kp.r[j] = kp.r[j + 1]; kp.i[j] = kp.i[j + 1]; }
            }
            const uint32_t h1 = an.v[2], h2 = an.v[3], h256 = an.v[4], h512 = an.v[5], h1024 = an.v[6];
            cpair p[11];
            p[0] = {an.v[0], an.v[1]};
            p[1] = pmul(p[0], h2); p[2] = pmul(p[0], h1); p[3] = pmul(p[1], h1);
            p[4] = pmul(p[0], h256); p[5] = pmul(p[1], h256); p[6] = pmul(p[0], h512); p[7] = pmul(p[4], h512);
            p[8] = pmul({__byte_perm(p[0].r, p[4].r, 0x5410), __byte_perm(p[0].i, p[4].i, 0x5410)}, h1024);
            p[9] = pmul(p[8], h512); p[10] = pmul(p[8], h1024);
#pragma unroll
            for (int j = 0; j < 3; j++) {
                const uint32_t a = tb + 8192 + (((3 * half + j) ^ sw) << 4);
                sts128(a, make_uint4(p[4 * j].r, p[4 * j + 1].r, p[4 * j + 2].r, p[j < 2 ? 4 * j + 3 : 10].r));
                sts128(a + 4096, make_uint4(p[4 * j].i, p[4 * j + 1].i, p[4 * j + 2].i, p[j < 2 ? 4 * j + 3 : 10].i));
            }
            an = kg_anchor_hi(kp, sel, dt, cs);
        }
        if (c == 0) TS(24);
        if (c == 3) TS(25);
        fence_async_smem();
        wg_wait<0>();
        named_bar(5 + wg, 128);
        wg_fence();
#pragma unroll
        for (int k = 0; k < 4; k++) wgmma_kg(acc, da + k * 128, da + 512 + k * 128, 1);
        wg_commit();
        tb += flip; da += flip >> 4; flip = -flip;
    }
    const bool up = warp & 2;
    const int r = 2 * wg + up, lo0 = 16 * half + (lane >> 2);
    const uint32_t o = dump + r * KG_RES + lo0 * 52 + 4 * (lane & 3);
    const float ci = __uint_as_float(lds32(s2u(&ks->cinv[r])));
    const float ds = (lane == 0 && warp <= 8 && !half) ? bf_lo(kp.ds) : 0.f;
    TS(26);
    wg_wait<0>();
    float v[12], m = 0.f;
#pragma unroll
    for (int j = 0; j < 12; j++) { v[j] = fmaf(ci, up ? acc[12 + j] : acc[j], j ? 0.f : ds); m = fmaxf(m, fabsf(v[j])); }
    const uint32_t mm = __reduce_max_sync(~0u, __float_as_uint(m));
    if (lane == 0) asm volatile("red.shared.max.u32 [%0], %1;" ::"r"(s2u(&ks->kmax[r])), "r"(mm) : "memory");
    named_bar(5 + wg, 128);
    const float mx = __uint_as_float(lds32(s2u(&ks->kmax[r]))) + (wg == 2 ? __uint_as_float(lds32(s2u(&ks->kmax[r ^ 1]))) : 0.f);
    const uint32_t e = min(max(__float_as_uint(mx) >> 23, 4u), 250u);
    const float sc = __uint_as_float((253u - e) << 23);
    if (lane == 0) ks->kexp[r] = e;
#pragma unroll
    for (int j = 0; j < 6; j++) sts32(o + (j & 1) * 416 + (j >> 1) * 16, pack2h(v[2 * j] * sc, v[2 * j + 1] * sc));
}
#define F_STAG 4
__device__ __forceinline__ void wgmma_h64_rs(uint32_t (&d)[16], const uint4& a, uint64_t db, int scale_d) {
    asm volatile("{\n.reg .pred p;\nsetp.ne.b32 p, %21, 0;\n"
                 "wgmma.mma_async.sync.aligned.m64n64k16.f16.f16.f16 {%0,%1,%2,%3,%4,%5,%6,%7,%8,%9,%10,%11,%12,%13,%14,%15}, {%16,%17,%18,%19}, %20, p, 1, 1, 1;\n}\n"
                 : "+r"(d[0]), "+r"(d[1]), "+r"(d[2]), "+r"(d[3]), "+r"(d[4]), "+r"(d[5]), "+r"(d[6]), "+r"(d[7]), "+r"(d[8]), "+r"(d[9]),
                   "+r"(d[10]), "+r"(d[11]), "+r"(d[12]), "+r"(d[13]), "+r"(d[14]), "+r"(d[15])
                 : "r"(a.x), "r"(a.y), "r"(a.z), "r"(a.w), "l"(db), "r"(scale_d));
}
template <int TB>
__device__ __forceinline__ void wgmma_h32_rs(uint32_t (&d)[8], const uint4& a, uint64_t db, int scale_d) {
    asm volatile("{\n.reg .pred p;\nsetp.ne.b32 p, %13, 0;\n"
                 "wgmma.mma_async.sync.aligned.m64n32k16.f16.f16.f16 {%0,%1,%2,%3,%4,%5,%6,%7}, {%8,%9,%10,%11}, %12, p, 1, 1, %14;\n}\n"
                 : "+r"(d[0]), "+r"(d[1]), "+r"(d[2]), "+r"(d[3]), "+r"(d[4]), "+r"(d[5]), "+r"(d[6]), "+r"(d[7])
                 : "r"(a.x), "r"(a.y), "r"(a.z), "r"(a.w), "l"(db), "r"(scale_d), "n"(TB));
}
__device__ __forceinline__ void wgmma_s1(uint32_t (&d)[16], const uint4& a, uint64_t db, int scale_d) { wgmma_h64_rs(d, a, db, scale_d); }
__device__ __forceinline__ void wgmma_s1(uint32_t (&d)[8], const uint4& a, uint64_t db, int scale_d) { wgmma_h32_rs<1>(d, a, db, scale_d); }
__device__ __forceinline__ void wgmma_s4(float (&d)[32], const uint4& a, uint64_t db, uint32_t meta, int scale_d) {
    asm volatile("{\n.reg .pred p;\nsetp.ne.b32 p, %38, 0;\n"
                 "wgmma.mma_async.sp.sync.aligned.m64n64k32.f32.f16.f16 {%0,%1,%2,%3,%4,%5,%6,%7,%8,%9,%10,%11,%12,%13,%14,%15,%16,%17,%18,%19,%20,%21,%22,%23,%24,%25,%26,%27,%28,%29,%30,%31}, {%32,%33,%34,%35}, %36, %37, 0, p, 1, 1, 1;\n}\n"
                 : "+f"(d[0]), "+f"(d[1]), "+f"(d[2]), "+f"(d[3]), "+f"(d[4]), "+f"(d[5]), "+f"(d[6]), "+f"(d[7]), "+f"(d[8]), "+f"(d[9]), "+f"(d[10]), "+f"(d[11]), "+f"(d[12]), "+f"(d[13]), "+f"(d[14]), "+f"(d[15]), "+f"(d[16]), "+f"(d[17]), "+f"(d[18]), "+f"(d[19]), "+f"(d[20]), "+f"(d[21]), "+f"(d[22]), "+f"(d[23]), "+f"(d[24]), "+f"(d[25]), "+f"(d[26]), "+f"(d[27]), "+f"(d[28]), "+f"(d[29]), "+f"(d[30]), "+f"(d[31])
                 : "r"(a.x), "r"(a.y), "r"(a.z), "r"(a.w), "l"(db), "r"(meta), "r"(scale_d));
}
__device__ __forceinline__ void wgmma_s4(float (&d)[16], const uint4& a, uint64_t db, uint32_t meta, int scale_d) {
    asm volatile("{\n.reg .pred p;\nsetp.ne.b32 p, %22, 0;\n"
                 "wgmma.mma_async.sp.sync.aligned.m64n32k32.f32.f16.f16 {%0,%1,%2,%3,%4,%5,%6,%7,%8,%9,%10,%11,%12,%13,%14,%15}, {%16,%17,%18,%19}, %20, %21, 0, p, 1, 1, 1;\n}\n"
                 : "+f"(d[0]), "+f"(d[1]), "+f"(d[2]), "+f"(d[3]), "+f"(d[4]), "+f"(d[5]), "+f"(d[6]), "+f"(d[7]), "+f"(d[8]), "+f"(d[9]), "+f"(d[10]), "+f"(d[11]), "+f"(d[12]), "+f"(d[13]), "+f"(d[14]), "+f"(d[15])
                 : "r"(a.x), "r"(a.y), "r"(a.z), "r"(a.w), "l"(db), "r"(meta), "r"(scale_d));
}

__device__ __forceinline__ uint32_t& u4r(uint4& v, int i) { return i == 0 ? v.x : i == 1 ? v.y : i == 2 ? v.z : v.w; }

template <int NC>
__device__ __forceinline__ void fft_stage(const uint32_t (&u)[2][4], int c, uint32_t eo, int w, int lane) {
    const int mi = lane >> 3, mj = lane & 7;
    const uint32_t a = eo + (8 * w + mj) * 128 + (((4 * c + mi) ^ mj) << 4);
    stsm_x4(a, hadd(u[0][0], u[1][0]), hadd(u[0][1], u[1][1]), hadd(u[0][2], u[1][2]), hadd(u[0][3], u[1][3]));
    stsm_x4(NC == 2 ? a + 4096 : a ^ 64, hsub(u[0][0], u[1][0]), hsub(u[0][1], u[1][1]), hsub(u[0][2], u[1][2]), hsub(u[0][3], u[1][3]));
}
template <int NC>
__device__ __forceinline__ void kernel_stage(const uint4 (&ko)[2], uint32_t kt, uint32_t eo, int w, int lane) {
    uint32_t u[2][2][4];
#pragma unroll
    for (int h = 0; h < 2; h++)
#pragma unroll
        for (int j = 0; j < 4; j++) {
            const uint32_t a0 = kt + (u4(ko[h], j) & 0xFFFF), a1 = kt + (u4(ko[h], j) >> 16);
#pragma unroll
            for (int c = 0; c < 2; c++)
                asm volatile("{\n.reg .b16 a, b;\nld.shared.b16 a, [%1];\nld.shared.b16 b, [%2];\nmov.b32 %0, {a, b};\n}"
                             : "=r"(u[c][h][j]) : "r"(a0 + c * KG_RES), "r"(a1 + c * KG_RES) : "memory");
            if (NC == 1) u[0][h][j] = hadd(u[0][h][j], u[1][h][j]);
        }
#pragma unroll
    for (int c = 0; c < NC; c++) fft_stage<NC>(u[c], c, eo, w, lane);
}

template <int NC, bool SHEAR, class Mid>
__device__ __forceinline__ void fft_forward(const uint4 (&a1)[4], const uint4 (&tw)[4], uint32_t eo, uint32_t s2, uint32_t (&X)[NC][2][8], Mid mid) {
    uint32_t dr[8 * NC], di[8 * NC];
    const uint64_t de = mkdesc(eo, 4096, 1024, 1), d2 = mkdesc(s2, 16, 1024, 1);
    wg_fence();
    wgmma_s1(dr, a1[0], de, 0);
    wgmma_s1(di, a1[2], de + (NC == 2 ? 256 : 4), 0);
    wgmma_s1(dr, a1[1], de + 128, 1);
    wgmma_s1(di, a1[3], de + (NC == 2 ? 384 : 132), 1);
    wg_commit();
    mid();
    wg_wait<0>();
#pragma unroll
    for (int c = 0; c < NC; c++) {
        uint4 zr[2], zi[2];
#pragma unroll
        for (int p = 0; p < 2; p++)
#pragma unroll
            for (int i = 0; i < 4; i++) {
                const uint32_t r = dr[8 * c + 4 * p + i], m = di[8 * c + 4 * p + i], tr = u4(tw[p], i), ti = u4(tw[2 + p], i);
                if (SHEAR) {
                    const uint32_t r1 = hfma(tr, m, r), m1 = hfma(ti, r1, m);
                    u4r(zr[p], i) = hfma(tr, m1, r1); u4r(zi[p], i) = m1;
                } else {
                    u4r(zr[p], i) = hfms(m, ti, hmul(r, tr));
                    u4r(zi[p], i) = hfma(m, tr, hmul(r, ti));
                }
            }
        wg_fence();
        wgmma_h32_rs<0>(X[c][0], zi[0], d2 + 2, 0);
        wgmma_h32_rs<0>(X[c][1], zi[1], d2 + 6, 0);
        wgmma_h32_rs<0>(X[c][0], zr[0], d2, 1);
        wgmma_h32_rs<0>(X[c][1], zr[1], d2 + 4, 1);
        wg_commit();
    }
}

template <int NC, class Idle, class Ready, class Staged>
__device__ __forceinline__ void conv_wg(int ch0, int layer, uint32_t eo, uint32_t zb, uint32_t s23, uint32_t kexp, uint32_t st, uint32_t sbar,
                                        int warp, int lane, uint4 (&a1)[4], uint4 (&tw)[4], Idle idle, Ready ready, Staged staged TS_ARG) {
    const int wg = warp >> 2, w = warp & 3, t = 32 * w + lane, g = lane >> 2, q = lane & 3, mi = lane >> 3, mj = lane & 7;
    auto F = [](uint32_t x) { return __uint_as_float(x); };
    uint32_t KH[NC][2][8];
    TS(2);
    fft_forward<NC, false>(a1, tw, eo, s23, KH, [] {});
    named_bar(1 + wg, 128);
    uint4 a4[4];
    if (NC == 2) {
#pragma unroll
        for (int i = 0; i < 4; i++) { tw[i] = ldg_tab(4 + i, t); a4[i] = ldg_tab(12 + i, t); }
    }
    wg_wait<0>();
    TS(4);
    idle();
    uint2 x[NC][2][2];
    const int ra[2] = {16 * (8 * w + g) + 4 * q, 16 * (63 - 8 * w - g) + 4 * q};
    {
        uint4 s[2][2][2];
        if (NC == 1) {
            TS(1);
#pragma unroll
            for (int i = 0; i < 8; i++) s[i >> 2][(i >> 1) & 1][i & 1] = make_uint4(layer, 0, 0, 0);
            int spin = 0;
            uint32_t bad;
            do {
                bad = 0;
#pragma unroll
                for (int i = 0; i < 8; i++) {
                    uint4& v = s[i >> 2][(i >> 1) & 1][i & 1];
                    if (((v.x ^ layer) & 1u) == 0) v = ld_ll4((const uint4*)(g_fs[i & 1] + 1024 * ((i >> 1) & 1) + ra[i >> 2]));
                }
#pragma unroll
                for (int i = 0; i < 8; i++) bad |= ~(s[i >> 2][(i >> 1) & 1][i & 1].x ^ layer);
            } while ((bad & 1u) && ++spin < (1 << 18));
#pragma unroll
            for (int i = 0; i < 8; i++) sts128(st + i * 2048 + t * 16, s[i >> 2][(i >> 1) & 1][i & 1]);
            __syncwarp();
            if (lane == 0) mbar_arrive(sbar + 8 * w);
            TS(14);
        }
        ready();
        TS(5);
#pragma unroll
        for (int i = 0; i < 4 * NC; i++) x[i >> 2][(i >> 1) & 1][i & 1] = ldg64(g_x1T + (size_t)(ch0 + (i >> 2)) * XP + 1024 * (i & 1) + ra[(i >> 1) & 1]);
        TS(6);
        if (NC == 2) {
            mbar_wait(sbar + 8 * w, 0);
#pragma unroll
            for (int i = 0; i < 8; i++) s[i >> 2][(i >> 1) & 1][i & 1] = lds128(st + i * 2048 + t * 16);
        }
        if (F_STAG == 1 && NC == 2 && wg == 1) named_bar(10 + w, 64);
        TS(7);
#pragma unroll
        for (int c = 0; c < NC; c++) {
            uint32_t u[2][4];
#pragma unroll
            for (int h = 0; h < 2; h++)
#pragma unroll
                for (int j = 0; j < 4; j++) {
                    const uint4 &a = s[h][j >> 1][0], &b = s[h][j >> 1][1];
                    const uint32_t xv = (j & 1) ? x[c][h][j >> 1].y : x[c][h][j >> 1].x;
                    u[h][j] = pack2h(fmaf(bf_lo(xv), F(u4(a, 2 * (j & 1))), F(u4(b, 2 * (j & 1)))), fmaf(bf_hi(xv), F(u4(a, 2 * (j & 1) + 1)), F(u4(b, 2 * (j & 1) + 1))));
                }
            fft_stage<NC>(u, c, eo, w, lane);
        }
    }
    if (F_STAG == 1 && NC == 2 && wg == 0) asm volatile("bar.arrive %0, 64;" ::"r"(10 + w) : "memory");
    TS(8);
    fence_async_smem();
    TS(9);
    if (NC == 1) {
#pragma unroll
        for (int i = 0; i < 4; i++) { tw[i] = ldg_tab(4 + i, t); a4[i] = ldg_tab(12 + i, t); }
    }
    staged();
    named_bar(1 + wg, 128);
    uint32_t X[NC][2][8], Y[NC][2][8];
    fft_forward<NC, true>(a1, tw, eo, s23, X, [&] { TS(3); if (F_STAG >= 2 && NC == 2 && wg == 1) named_bar(10 + w, 64); });
    if (F_STAG == 2 && NC == 2 && wg == 0) asm volatile("bar.arrive %0, 64;" ::"r"(10 + w) : "memory");
    TS(10);
    const uint64_t d3 = mkdesc(s23 + 4096, 16, 1024, 1);
#pragma unroll
    for (int c = 0; c < NC; c++) {
        wg_wait<NC - 1>();
        TS(11 + c);
        uint4 pr[2], pi[2];
#pragma unroll
        for (int i = 0; i < 4; i++) {
            const uint32_t er = X[c][0][i], ei = X[c][0][4 + i], orr = X[c][1][i], oi = X[c][1][4 + i];
            const uint32_t ar = KH[c][0][i], ai = KH[c][0][4 + i], br = KH[c][1][i], bi = KH[c][1][4 + i];
            u4r(pr[0], i) = hfms(bi, oi, hfma(br, orr, hfms(ai, ei, hmul(ar, er))));
            u4r(pi[0], i) = hfma(bi, orr, hfma(br, oi, hfma(ai, er, hmul(ar, ei))));
            u4r(pr[1], i) = hfms(ai, oi, hfma(ar, orr, hfms(bi, ei, hmul(br, er))));
            u4r(pi[1], i) = hfma(ai, orr, hfma(ar, oi, hfma(bi, er, hmul(br, ei))));
        }
        if (F_STAG == 3 + c && NC == 2 && wg == 0) asm volatile("bar.arrive %0, 64;" ::"r"(10 + w), "r"(pr[0].x ^ pr[1].w ^ pi[0].y ^ pi[1].z) : "memory");
        wg_fence();
        wgmma_h32_rs<0>(Y[c][0], pr[0], d3, 0);
        wgmma_h32_rs<0>(Y[c][1], pr[1], d3 + 4, 0);
        wgmma_h32_rs<0>(Y[c][0], pi[0], d3 + 2, 1);
        wgmma_h32_rs<0>(Y[c][1], pi[1], d3 + 6, 1);
        wg_commit();
    }
#pragma unroll
    for (int c = 0; c < NC; c++) {
        if (c + 1 < NC) wg_wait<1>(); else wg_wait<0>();
        TS(13 + c);
        uint32_t zr[2][4], zi[2][4];
#pragma unroll
        for (int p = 0; p < 2; p++)
#pragma unroll
            for (int i = 0; i < 4; i++) {
                const uint32_t r = Y[c][p][i], m = Y[c][p][4 + i], tr = u4(tw[p], i), ti = u4(tw[2 + p], i);
                const uint32_t r1 = hfms(tr, m, r), m1 = hfms(ti, r1, m);
                zr[i & 1][2 * p + (i >> 1)] = hfms(tr, m1, r1);
                zi[i & 1][2 * p + (i >> 1)] = m1;
            }
        const int kr = 4 * (mj >> 1) + (mj & 1) + 2 * (mj >> 2), ki = kr ^ 2;
#pragma unroll
        for (int h = 0; h < 2; h++) {
            const uint32_t a = zb + (2 * w + h) * 2048;
            stsm_x4(a + ki * 128 + (((4 * c + mi) ^ (ki & 7)) << 4), zi[h][0], zi[h][1], zi[h][2], zi[h][3]);
            stsm_x4(a + kr * 128 + (((4 * c + mi) ^ (kr & 7)) << 4), zr[h][0], zr[h][1], zr[h][2], zr[h][3]);
        }
    }
    TS(15);
    fence_async_smem();
    TS(16);
    named_bar(1 + wg, 128);
    TS(17);
    float acc[16 * NC];
    const uint64_t dz = mkdesc(zb, 4096, 1024, 1);
    wg_fence();
#pragma unroll
    for (int ks = 0; ks < 4; ks++) wgmma_s4(acc, a4[ks], dz + ks * 256, 0x44EEEE44u, ks > 0);
    wg_commit();
    uint32_t oscale[NC];
#pragma unroll
    for (int c = 0; c < NC; c++) oscale[c] = (lds32(kexp + 4 * c) + 3u) * 0x00800080u;
    bf16* dst = g_x2T[layer] + (size_t)ch0 * XP;
    wg_wait<0>();
    TS(18);
#pragma unroll
    for (int c = 0; c < NC; c++)
#pragma unroll
        for (int p = 0; p < 2; p++) {
            uint32_t r[2][2];
#pragma unroll
            for (int j = 0; j < 2; j++) {
                const float* d = acc + 4 * (4 * c + 2 * p + j);
                const uint32_t y0 = pack2(d[0] + d[2], d[1] + d[3]), y1 = pack2(d[0] - d[2], d[1] - d[3]);
                asm("fma.rn.bf16x2 %0, %1, %2, %3;" : "=r"(r[0][j]) : "r"(y0), "r"(oscale[c]), "r"(j ? x[c][0][p].y : x[c][0][p].x));
                asm("fma.rn.bf16x2 %0, %1, %2, %3;" : "=r"(r[1][j]) : "r"(y1), "r"(oscale[c]), "r"(j ? x[c][1][p].y : x[c][1][p].x));
            }
#pragma unroll
            for (int h = 0; h < 2; h++)
                st_ll((unsigned long long*)(dst + c * XP + 1024 * p + ra[h]), r[h][0] ? r[h][0] : 0x80000000u, r[h][1]);
        }
    TS(19);
}

#define Q_SCHED 3
#define Q_WAITFOR(it) (Q_SCHED == 0 ? (it) - 2 : Q_SCHED == 1 ? ((it) == 3 ? 1 : 0) : Q_SCHED == 2 ? -1 : (it) - 1)
#define Q_S0 8
#define Q_ROT 0
#define O_ROT 0
#define A_HPOS 1
#define A_CSPRE 2
#define R_CONS 200
#define F_PRE 4
#define FIN_DELAY 500
#define T_PF 1
#define K_CSUN 1
constexpr int K_CSU = K_CSUN;
#define G_MAP 1
#define O_TPOS 5
#define O_PASS 3
#define O_DEPTH 4
#define FIN_SLEEP 0
constexpr int Q_ST = 4;
constexpr int Q_AB = 16384, Q_BB = 30720, Q_SB = Q_AB + Q_BB;
constexpr int Q_EROW = 336;
constexpr int Q_ESLOT = 8 * Q_EROW;
constexpr int Q_EOFF = Q_ST * Q_SB;
constexpr int Q_KG = 2 * Q_SB;
static_assert(3 * Q_ESLOT <= 8192 && Q_KG + KG_TABLES <= Q_EOFF + 4096, "exchange slots, kernel generation");
constexpr int F_EO = Q_EOFF, F_S23 = F_EO + 2 * 8192 + 4096, Q_KDUMP = F_S23 + 8192;
constexpr int Q_SMEM = Q_KDUMP + 6 * KG_RES + TS_SMEM;
__host__ __device__ constexpr int w_grp(int j) { return j < 7 ? 2 * Q_SB + j * 12800 : 20480; }
constexpr int W_RES = 0;

constexpr int Q_ZERO = Q_EOFF + 4096, Q_WOT = Q_EOFF + 8320;

__device__ unsigned g_epoch;
__device__ __align__(1024) unsigned g_bar[4][16][32];
__device__ __align__(1024) uint4 g_wop[8][80][10][8];
__device__ __align__(1024) uint4 g_csp[8][16][96];
__device__ __align__(1024) uint4 g_stp[16][8][64];
__device__ __align__(1024) uint4 g_sp2[16][8][8][8];
__device__ __align__(1024) uint4 g_halo[128][2][5][32];
__device__ __align__(1024) uint4 g_of[8][16][8][5][32];

struct Bars { uint64_t full[Q_ST], empty[Q_ST], wfull[3], ex[7], res, go, prep, ardy, hdone, fdone, idx, att1, pass, staged[2], st[4], kfree; };
constexpr int NBAR = sizeof(Bars) / 8;
__host__ __device__ constexpr int bar_count(int i) {
#define BAR_IS(f) (i == offsetof(Bars, f) / 8)
    return (i >= 4 && i < 8) ? 16 : (BAR_IS(go) || (i >= offsetof(Bars, att1) / 8 && i < offsetof(Bars, st) / 8)) ? 4 : BAR_IS(prep) ? 96 :
           BAR_IS(hdone) ? 6 : BAR_IS(fdone) ? 3 : BAR_IS(kfree) ? 24 : 1;
}
__device__ __forceinline__ void grid_wait(const unsigned* c, int n, unsigned target, int lane) {
    const unsigned* p = c + 32 * min(lane, n - 1);
    unsigned v;
    int spin = 0;
    do { asm volatile("ld.relaxed.gpu.global.u32 %0, [%1];" : "=r"(v) : "l"(p) : "memory"); } while (!__all_sync(~0u, (int)(v - target) >= 0) && ++spin < (1 << 18));
    fence_acquire();
}
__device__ __forceinline__ void grid_arrive(unsigned* c) {
    fence_release();
    asm volatile("red.relaxed.gpu.global.add.u32 [%0], 1;" ::"l"(c) : "memory");
}

#define TMAP(n) ([] { const CUtensorMap* p_; asm volatile("{\n.reg .b64 t;\nmov.b64 t, fused_kernel_param_" #n ";\ncvta.param.u64 %0, t;\n}" : "=l"(p_)); return p_; }())
extern "C" __global__ void __launch_bounds__(384, 1)
fused_kernel(const SsmParams sp, const __grid_constant__ CUtensorMap mX0, const __grid_constant__ CUtensorMap mX1, const __grid_constant__ CUtensorMap mW,
             const __grid_constant__ CUtensorMap mWr,
             const __grid_constant__ CUtensorMap mRes0, const __grid_constant__ CUtensorMap mRes1, const __grid_constant__ CUtensorMap mOut,
             const __grid_constant__ CUtensorMap mWo, const __grid_constant__ CUtensorMap mFin, const __grid_constant__ CUtensorMap mResA) {
    extern __shared__ __align__(1024) char smraw[];
    __shared__ __align__(8) Bars s_bar[2];
    __shared__ __align__(16) float s_cs[240], s_mean[2][64], s_rstd[2][72];
    __shared__ KgShared s_kg;
    __shared__ uint32_t s_epoch;
    const uint32_t sb = s2u(smraw);
    int tid, warp, lane, bx, rank, blk, hg, rot, c0;
    int role;
    {
        const int c = blockIdx.x >> 1, d = c - 41, r = d >= 21 ? 3 : d >= 14 ? 2 : d >= 7 ? 1 : 0;
        const int gp = c < 4 ? 0 : c <= 40 ? (c + 7) & 7 : d - 7 * r + 1;
        const int k = c < 4 ? c : c <= 40 ? (c >> 3) + (gp == 0 ? 3 : gp >= 3 && gp < 7 ? 0 : -1) : (gp >= 3 ? 5 : 4) + r;
        role = G_MAP == 1 ? 16 * k + 2 * gp + (blockIdx.x & 1) : G_MAP == 2 ? 16 * gp + 2 * k + (blockIdx.x & 1) : blockIdx.x;
    }
    auto indices = [&] {
        asm volatile("mov.u32 %0, %%tid.x;" : "=r"(tid));
        asm volatile("mov.u32 %0, %1;" : "=r"(bx) : "r"(role));
        warp = __shfl_sync(~0u, tid >> 5, 0); lane = tid & 31;
        rank = bx & 1; blk = bx & 15; hg = bx >> 4;
        const int u = ((blk >> 1) + hg) & 7;
        rot = (5 * u) >> 2; c0 = 16 * (u & 3);
    };
    indices();
    TS_DECL;
    TS_BEGIN;
#define EPOCH lds32(s2u(&s_epoch))
    int layer = 0;
    uint32_t bars = s2u(s_bar);
#define BAR(f) (bars + (uint32_t)offsetof(Bars, f))
    auto chunk = [&](int it) { return Q_ROT ? it + rot - (it + rot >= 10 ? 10 : 0) : it < 2 ? rot + it : it - 2 < rot ? it - 2 : it; };
    auto osrc_of = [&](int j) { return O_ROT ? (hg + j) & 7 : j == 0 ? hg : j - 1 < hg ? j - 1 : j; };
    auto issue_w = [&](uint32_t bb, int it, int half) {
        const int s = it & (Q_ST - 1);
        const uint32_t fb = bb + 8 * s, db = sb + s * Q_SB + Q_AB + half * 15360;
        const int k0 = chunk(it) * 64 + half * 32;
#pragma unroll
        for (int p = 0; p < 3; p++) tma2d_mc(db + p * 4096, TMAP(3), p * DM + hg * 80, k0, fb, 3);
        tma3d_mc(db + 12288, TMAP(4), hg * 80 + 64, k0, 0, fb, 3);
    };
    auto issue_x = [&](int it) {
        const int s = it & (Q_ST - 1), kc = chunk(it);
        mbar_expect(BAR(full) + 8 * s, Q_SB);
        tma3d(sb + s * Q_SB, TMAP(1) + layer, (layer ? blk : kc) * 64, (layer ? kc : blk) * 64, 0, BAR(full) + 8 * s);
    };
    auto clear_fin = [&](uint32_t zero) {
#pragma unroll 1
        for (int i = 0; i < 5; i++) bulk_s2g(g_x2T[1] + (bx * 5 + i) * XP, zero, SEQ * 2);
        bulk_commit();
    };
    {
        KgParams kp;
        kgen_load(kp, bx * 5, warp, lane, sp);
        if (warp < 8) {
            cluster_arrive_relaxed();
        } else {
            const int t2 = tid - 256;
            if (elect_one()) {
                if (warp < 10) { prefetch_tmap(TMAP(3)); prefetch_tmap(TMAP(4)); } else prefetch_tmap(warp == 10 ? TMAP(1) : TMAP(8));
                const uint32_t b0 = bars + (warp >= 10 ? sizeof(Bars) : 0);
                if (warp & 1) {
#pragma unroll
                    for (int i = 0; i < NBAR / 2; i++) mbar_init(b0 + i * 8, bar_count(i));
                } else {
#pragma unroll
                    for (int i = NBAR / 2; i < NBAR; i++) mbar_init(b0 + i * 8, bar_count(i));
                }
                fence_mbar_init();
            }
            __syncwarp();
            cluster_arrive_relaxed();
            TS(29);
            const uint32_t epoch0 = ldg32(&g_epoch);
            sts128(sb + Q_ZERO + t2 * 16, make_uint4(0, 0, 0, 0)); sts128(sb + Q_ZERO + 2048 + t2 * 16, make_uint4(0, 0, 0, 0));
            cluster_wait();
            TS(27);
            if (elect_one()) {
                if (warp < 10) {
                    issue_w(BAR(full), warp - 8, rank);
                } else if (warp == 10) {
                    issue_x(0); issue_x(1);
                    prefetch_l2((const char*)c_fft + bx * (sizeof(c_fft) / 128), sizeof(c_fft) / 128);
                } else {
                    mbar_expect(BAR(idx), 8192 + 6400);
                    asm volatile("cp.async.bulk.tensor.4d.shared::cluster.global.mbarrier::complete_tx::bytes [%0], [%1, {0, 0, %3, %4}], [%2];"
                                 ::"r"(sb + Q_WOT), "l"(TMAP(8)), "r"(BAR(idx)), "r"(10 * hg), "r"(5 * blk) : "memory");
                    bulk_g2s(sb + F_S23, c_fft + 18 * 512, 8192, BAR(idx));
                }
            }
            __syncwarp();
            if (t2 == 0) s_epoch = epoch0;
            TS(30);
        }
        indices();
        kgen_tables(kp, sb + Q_KG, sb + Q_KDUMP, &s_kg, warp, lane TS_PASS);
        if (warp < 8) cluster_wait();
        __syncwarp();
        if (lane == 0) { mbar_arrive_cta(BAR(kfree), 0); mbar_arrive_cta(BAR(kfree), 1); }
        if (warp >= 8) {
            const int t2 = tid - 256;
            float csum[10];
            if (warp == 11 && elect_one()) clear_fin(sb + Q_ZERO);
            __syncwarp();
            if (t2 < 64) stg128(&g_sp2[blk][hg][0][0] + t2, make_uint4(0, 0, 0, 0));
            if (t2 >= 120) stg128((uint4*)g_fs + 8 * bx + t2 - 120, make_uint4(0, 0, 0, 0));
#pragma unroll
            for (int i = 0; i < 3; i++)
                if (t2 + 128 * i < 320) stg128(&g_halo[bx][0][0][0] + t2 + 128 * i, make_uint4(0, 0, 0, 0));
            if (warp == 8) asm volatile("bar.arrive 13, 128;" ::: "memory"); else named_bar(13, 128);
            if (warp > 8) {
                const int hw = warp - 9, mi = lane >> 3, mj = lane & 7;
                mbar_wait(BAR(idx), 0);
                if (hw == 2 && elect_one()) { bulk_s2g(&g_wop[hg][5 * blk], sb + Q_WOT, 6400); bulk_commit(); }
                __syncwarp();
                mbar_wait(BAR(full), 0);
                mbar_wait(BAR(full) + 8, 0);
#pragma unroll
                for (int f = 0; f < 10; f++) csum[f] = 0.f;
#pragma unroll K_CSU
                for (int G = 0; G < 5; G++) {
                    const int row = c0 + 40 * rank + 8 * G + mj;
                    const uint32_t b = sb + (row >> 6) * Q_SB + Q_AB + ((row >> 5) & 1) * 15360;
                    uint32_t r[10];
                    ldsm_x4_t(r[0], r[1], r[2], r[3], b + hw * 4096 + (row & 31) * 128 + ((mi ^ mj) << 4));
                    ldsm_x4_t(r[4], r[5], r[6], r[7], b + hw * 4096 + (row & 31) * 128 + (((4 + mi) ^ mj) << 4));
                    ldsm_x2_t(r[8], r[9], b + 12288 + hw * 1024 + (row & 31) * 32 + (((mi & 1) ^ (mj >> 2)) << 4));
#pragma unroll
                    for (int f = 0; f < 10; f++) csum[f] += bf_lo(r[f]) + bf_hi(r[f]);
                }
                const int q = lane & 3;
                float t[3];
#pragma unroll
                for (int j = 0; j < 3; j++) {
                    float v[4];
#pragma unroll
                    for (int k = 0; k < 4; k++) v[k] = 4 * j + k < 10 ? csum[4 * j + k] : 0.f;
                    const float a0 = ((q & 2) ? v[2] : v[0]) + __shfl_xor_sync(~0u, (q & 2) ? v[0] : v[2], 2);
                    const float a1 = ((q & 2) ? v[3] : v[1]) + __shfl_xor_sync(~0u, (q & 2) ? v[1] : v[3], 2);
                    t[j] = ((q & 1) ? a1 : a0) + __shfl_xor_sync(~0u, (q & 1) ? a0 : a1, 1);
                }
                st_ll4(&g_csp[hg][blk][tid - 288], ~EPOCH & 1u, __float_as_uint(t[0]), __float_as_uint(t[1]), __float_as_uint(t[2]));
            }
        }
        TS(1);
    }

    uint4 fa1[4], ftw[4];
    auto conv_tables = [&] {
#pragma unroll
        for (int i = 0; i < 4; i++) { fa1[i] = ldg_tab(i, tid & 127); ftw[i] = ldg_tab(8 + i, tid & 127); }
    };
    auto conv_done = [&] {
        if (layer == 0) {
            named_bar(1 + (warp >> 2), 128);
            if ((tid & 127) == 0) {
                mbar_arrive(BAR(fdone));
                grid_arrive(g_bar[2][hg]);
            }
            __syncwarp();
        }
        TS(20);
    };
    if (warp >= 8) {
    asm volatile("setmaxnreg.dec.sync.aligned.u32 %0;" ::"n"(504 - 2 * R_CONS));
#pragma unroll 1
    for (; layer < 2; layer++, bars += sizeof(Bars)) {
        indices();
        TS_PHASE(2 * layer);
        if (warp == 8) {
            if (layer) {
                grid_wait(g_bar[2][0], 8, 48 * (EPOCH + 1), lane);
                mbar_wait(BAR(fdone) - sizeof(Bars), 0);
                fence_async_global();
                TS(1);
            }
            if (elect_one()) {
#pragma unroll 1
                for (int it = layer ? 0 : 2; it < 10; it++) {
                    if (it >= Q_ST) mbar_wait(BAR(empty) + 8 * (it & (Q_ST - 1)), ((it >> 2) - 1) & 1);
                    else if (layer == 0) mbar_wait(BAR(kfree), 0);
                    else if (it > 0 && Q_WAITFOR(it) >= 0) mbar_wait(BAR(full) + 8 * Q_WAITFOR(it), 0);
                    if (it == Q_ST) mbar_wait(BAR(hdone), 0);
                    issue_x(it);
                    if (layer == 0 || it >= F_PRE) issue_w(BAR(full), it, rank);
                }
                if (T_PF) { prefetch_tmap(TMAP(5) + layer); prefetch_tmap(TMAP(7)); prefetch_tmap(TMAP(10)); }
                if (layer == 0) { mbar_wait(BAR(prep), 0); fence_async_global(); }
#pragma unroll 1
                for (int j = 0; j < 8; j++) {
                    const int b = (j + 1) >> 2;
                    const uint32_t fb = BAR(wfull) + 8 * b;
                    if (j == 0 || j == 3 || j == 7) {
                        mbar_wait(BAR(empty) + 8 * ((2 + b) & 3), b < 2);
                        TS(11 + b);
                        mbar_expect(fb, (b == 0 ? 3 : b == 1 ? 4 : 1) * 12800);
                    }
                    bulk_g2s_mc(sb + w_grp(j) + rank * 6400, &g_wop[hg][osrc_of(j) * 10 + rank * 5], 6400, fb, 3);
                }
                mbar_expect(BAR(res), 20480);
                if (layer) {
                    tma3d(sb + W_RES, TMAP(6), blk * 64, hg * 80, 0, BAR(res));
                } else {
#pragma unroll 1
                    for (int p = 0; p < 2; p++) {
                        tma3d(sb + W_RES + p * 10240, TMAP(10), hg * 80, blk * 64, p, BAR(res));
                        tma3d(sb + W_RES + p * 10240 + 8192, TMAP(5), hg * 80 + 64, blk * 64, p, BAR(res));
                    }
                }
            }
            __syncwarp();
        } else {
            const int ht = tid - 288, hw = warp - 9, mi = lane >> 3, mj = lane & 7, g = lane >> 2, q = lane & 3;
            auto F = [](uint32_t x) { return __uint_as_float(x); };
            auto U = [](float x) { return __float_as_uint(x); };
            const uint32_t lb = layer ^ 1, eb = ~EPOCH & 1u;
            mbar_wait(BAR(full), 0);
            mbar_wait(BAR(full) + 8, 0);
            if (ht == 0) TSX(2, 2);
            uint32_t xf[3][20];
#pragma unroll
            for (int i = 0; i < 3; i++) {
                const int tile = min(hw + 3 * i, 7);
#pragma unroll
                for (int k = 0; k < 5; k++) {
                    const int ch = c0 + 16 * k + 8 * (mi >> 1), tok = 16 * (tile & 3) + 8 * (mi & 1);
                    const uint32_t a = sb + (ch >> 6) * Q_SB + (tile >> 2) * 8192;
                    if (layer == 0) ldsm_x4(xf[i][4 * k], xf[i][4 * k + 1], xf[i][4 * k + 2], xf[i][4 * k + 3], a + (tok + mj) * 128 + ((((ch & 63) >> 3) ^ mj) << 4));
                    else ldsm_x4_t(xf[i][4 * k], xf[i][4 * k + 1], xf[i][4 * k + 2], xf[i][4 * k + 3], a + ((ch & 63) + mj) * 128 + (((tok >> 3) ^ mj) << 4));
                }
            }
            fence_async_smem();
            __syncwarp();
            if (lane == 0) { mbar_arrive_cta(BAR(hdone), 0); mbar_arrive_cta(BAR(hdone), 1); }
            if (ht == 0) TSX(2, 3);
            if (layer == 0) {
                if (hw == 2 && elect_one()) { bulk_wait(); fence_async_global(); grid_arrive(g_bar[3][hg]); }
                __syncwarp();
                mbar_wait(BAR(kfree), 0);
            }
            if (ht == 0) TSX(2, 8);
#pragma unroll 1
            for (int tile = hw; tile < 8; tile += 3) {
                float a[4] = {0.f, 0.f, 0.f, 0.f};
#pragma unroll
                for (int j = 0; j < 20; j++) {
                    const float lo = bf_lo(xf[0][j]), hi = bf_hi(xf[0][j]);
                    a[2 * (j & 1)] += lo + hi; a[2 * (j & 1) + 1] = fmaf(lo, lo, fmaf(hi, hi, a[2 * (j & 1) + 1]));
                    xf[0][j] = xf[1][j]; xf[1][j] = xf[2][j];
                }
#pragma unroll
                for (int j = 0; j < 4; j++) { a[j] += __shfl_xor_sync(~0u, a[j], 1); a[j] += __shfl_xor_sync(~0u, a[j], 2); }
                if (q == 0) st_ll4(&g_stp[blk][hg][8 * tile + g], (U(a[0]) & ~1u) | lb, U(a[1]), U(a[2]), U(a[3]));
            }
            if (ht == 0) TSX(2, 4);
            if (layer == 0) {
                float t[4] = {0.f, 0.f, 0.f, 0.f};
                uint4 v[16];
                int spin = 0;
                uint32_t bad;
                do {
                    bad = 0;
#pragma unroll
                    for (int j = 0; j < 16; j++) v[j] = ld_ll4(&g_csp[hg][j][ht]);
#pragma unroll
                    for (int j = 0; j < 16; j++) bad |= v[j].x ^ eb;
                } while ((bad & 1u) && ++spin < (1 << 18));
#pragma unroll
                for (int j = 0; j < 16; j++) { t[0] += F(v[j].y); t[1] += F(v[j].z); t[2] += F(v[j].w); }
#pragma unroll
                for (int j = 0; j < 3; j++) if (q + 4 * j < 10) s_cs[80 * hw + 20 * (g >> 1) + 2 * (q + 4 * j) + (g & 1)] = t[j];
                if (hw == 2) grid_wait(g_bar[3][0], 8, 16 * (EPOCH + 1), lane);
            }
            if (ht == 0) TSX(2, 15);
            if (ht < 80) {
                const bool halo = ht >= 64;
                const int p = halo ? (ht >> 3) & 1 : ht >> 5, i = halo ? (ht & 7) - 8 : 8 + 2 * (ht & 24) + (ht & 7);
                const uint4* src = &g_stp[halo && blk ? blk - 1 : blk][0][halo ? 32 * p + 24 + (ht & 7) : ht];
                uint4 v[8];
                int spin = 0;
                uint32_t bad;
                do {
                    bad = 0;
#pragma unroll
                    for (int j = 0; j < 8; j++) v[j] = ld_ll4(src + 64 * j);
#pragma unroll
                    for (int j = 0; j < 8; j++) bad |= v[j].x ^ lb;
                } while ((bad & 1u) && ++spin < (1 << 18));
                float t[4] = {0.f, 0.f, 0.f, 0.f};
#pragma unroll
                for (int j = 0; j < 8; j++) { t[0] += F(v[j].x); t[1] += F(v[j].y); t[2] += F(v[j].z); t[3] += F(v[j].w); }
                const uint32_t s0 = ln_finish_packed(t[0], t[1]), s1 = ln_finish_packed(t[2], t[3]);
                if (!halo) { s_mean[p][i - 8] = bf_hi(s0); s_mean[p][i] = bf_hi(s1); s_rstd[p][i] = frcp(bf_lo(s0)); }
                s_rstd[p][i + 8] = frcp(bf_lo(s1));
            }
            fence_acquire();
            mbar_arrive(BAR(prep));
            if (ht == 0) TSX(2, 5);
        }
        __syncwarp();
        TS_PHASE(2 * layer + 1);
        TS(0);
        indices();
        {
            const uint4 ko[2] = {ldg_tab(16, tid & 127), ldg_tab(17, tid & 127)};
            conv_tables();
            mbar_wait(BAR(att1), 0);
            kernel_stage<1>(ko, sb + Q_KDUMP + 4 * KG_RES, sb + F_EO + 2 * 8192, warp & 3, lane);
            fence_async_smem();
            named_bar(3, 128);
        }
        conv_wg<1>(5 * bx + 4, layer, sb + F_EO + 2 * 8192, sb + 2 * Q_SB, sb + F_S23, s2u(&s_kg.kexp[4]), sb + 3 * Q_SB, BAR(st), warp, lane, fa1, ftw,
        [&] {
            if (warp >= 10) {
                const int i = warp - 10;
                mbar_wait(BAR(staged) + 8 * i, 0);
                if (elect_one()) {
                    asm volatile("cp.async.bulk.tensor.2d.global.shared::cta.bulk_group [%0, {%2, %3}], [%1];"
                                 ::"l"(TMAP(7)), "r"(sb + W_RES + i * 10240), "r"(1024 * i + 64 * blk), "r"(hg * 80) : "memory");
                    bulk_commit();
                    bulk_wait();
                    fence_async_global();
                    grid_arrive(g_bar[layer][hg]);
                }
                __syncwarp();
            } else if (warp == 9) {
                auto F = [](uint32_t x) { return __uint_as_float(x); };
                mbar_wait(BAR(staged) + 8 * (hg >> 2), 0);
                const uint4* src = &g_sp2[blk][hg][0][0] + lane;
                uint4 a, b;
                int spin = 0;
                do { a = ld_ll4(src); b = ld_ll4(src + 32); } while (__any_sync(~0u, ~((a.x ^ layer) & (b.x ^ layer)) & 1u) && ++spin < (1 << 18));
                const bool up = lane & 8;
                const float s0 = F(a.x) + F(b.x), q0 = F(a.y) + F(b.y), s1 = F(a.z) + F(b.z), q1 = F(a.w) + F(b.w);
                float sm = (up ? s1 : s0) + __shfl_xor_sync(~0u, up ? s0 : s1, 8), sq = (up ? q1 : q0) + __shfl_xor_sync(~0u, up ? q0 : q1, 8);
                sm += __shfl_xor_sync(~0u, sm, 16); sq += __shfl_xor_sync(~0u, sq, 16);
                const float m = sm * (1.0f / DM), r = frsq(fmaxf(fmaf(sq, 1.0f / DM, fmaf(-m, m, 1e-5f)), 1e-5f));
                const uint32_t v = __float_as_uint(lane & 16 ? -m * r : r);
                const uint32_t v0 = __shfl_sync(~0u, v, 4 * lane), v1 = __shfl_sync(~0u, v, 4 * lane + 1), v2 = __shfl_sync(~0u, v, 4 * lane + 2), v3 = __shfl_sync(~0u, v, 4 * lane + 3);
                if (lane < 8) st_ll4((uint4*)(g_fs[lane >> 2] + 1024 * (hg >> 2) + 64 * blk + 16 * (hg & 3)) + (lane & 3), (v0 & ~1u) | (layer ^ 1), v1, v2, v3);
            }
            named_bar(3, 128);
        }, [&] { mbar_wait(BAR(ardy), 0); }, [&] {
            if (T_PF && tid == 352) prefetch_tmap(layer ? TMAP(9) : TMAP(2));
            if (layer == 0 && warp - 8 < F_PRE && elect_one()) issue_w(BAR(full) + sizeof(Bars), warp - 8, rank);
            __syncwarp();
        } TS_PASS);
        conv_done();
    }
    } else {
#pragma unroll 1
    for (; layer < 2; layer++, bars += sizeof(Bars)) {
    indices();
    TS_PHASE(2 * layer);
    const int wg = warp >> 2, w = warp & 3;
    const int mi = lane >> 3, mj = lane & 7, g = lane >> 2, q = lane & 3;
    TS(2);
    float acc[120];
#pragma unroll
    for (int i = 0; i < 120; i++) acc[i] = 0.f;
    auto release = [&](int it) {
        if (lane == 0) { mbar_arrive_cta(BAR(empty) + 8 * (it & (Q_ST - 1)), 0); mbar_arrive_cta(BAR(empty) + 8 * (it & (Q_ST - 1)), 1); }
    };
#pragma unroll 1
    for (int it = 0; it < 10; it++) {
        const int s = it & (Q_ST - 1);
        const uint32_t st = sb + s * Q_SB;
        const bool hold = wg == 1 && it == Q_S0;
        if (hold) {
            wg_wait<0>();
            release(it - 1);
            mbar_wait(BAR(go), 0);
        }
        mbar_wait(BAR(full) + 8 * (s), (it >> 2) & 1);
        if (it < 2) TS(3 + it);
        if (it == 6) TS(5);
        if (it == 9) TS(6);
        const uint64_t da = mkdesc(st + wg * 8192, 16, 1024, 1);
        const uint64_t db = mkdesc(st + Q_AB, 4096, 1024, 1);
        const uint64_t dr = mkdesc(st + Q_AB + 12288, 1024, 256, 3);
        if (layer == 0) {
            wg_fence();
#pragma unroll
            for (int ks = 0; ks < 4; ks++) {
                const int sc = 1;
                wgmma_n192<0, 1>(*(float(*)[96]) & acc[0], da + ks * 2, db + (ks >> 1) * 960 + (ks & 1) * 128, sc);
                wgmma_n48<0, 1>(*(float(*)[24]) & acc[96], da + ks * 2, dr + (ks >> 1) * 960 + (ks & 1) * 32, sc);
            }
            wg_commit();
        } else {
            wg_fence();
#pragma unroll
            for (int ks = 0; ks < 4; ks++) {
                const int sc = 1;
                wgmma_n192<1, 1>(*(float(*)[96]) & acc[0], da + ks * 128, db + (ks >> 1) * 960 + (ks & 1) * 128, sc);
                wgmma_n48<1, 1>(*(float(*)[24]) & acc[96], da + ks * 128, dr + (ks >> 1) * 960 + (ks & 1) * 32, sc);
            }
            wg_commit();
        }
        wg_wait<1>();
        if (it > 0 && !hold) release(it - 1);
    }
    if (wg == 0 && lane == 0) mbar_arrive(BAR(go));
    asm volatile("setmaxnreg.inc.sync.aligned.u32 %0;" ::"n"(R_CONS));
    mbar_wait(BAR(prep), 0);
    const uint32_t ob = layer ^ 1;
    const bool first = (blk == 0 && w == 0);
    const bool sel0 = (2 * q > g), sel1 = (2 * q + 1 > g);
    constexpr float SC = 0.22360679774997896f * 1.4426950408889634f;
    const float m0 = s_mean[wg][16 * w + g], m1 = s_mean[wg][8 + 16 * w + g];
    uint4 cs[3][5];
    auto cs_load = [&](int p) {
#pragma unroll
        for (int i = 0; i < 5; i++) cs[p][i] = lds128(s2u(&s_cs[80 * p + 20 * q + 4 * i]));
    };
    if (A_CSPRE >= 1) cs_load(1);
    if (A_CSPRE >= 2) cs_load(2);
    wg_wait<0>();
    if (A_CSPRE < 1) cs_load(1);
    if (A_CSPRE < 2) cs_load(2);
    TS(7);
    uint32_t ql[10], qh[10], kl[10], kh[10], vl[10], vh[10];
    auto fold = [&](int p, int f, int h) {
        const int j = (f < 8) ? 8 * p + f : 24 + 2 * p + (f - 8);
        const float c0 = __uint_as_float(u4(cs[p][f >> 1], 2 * (f & 1))), c1 = __uint_as_float(u4(cs[p][f >> 1], 2 * (f & 1) + 1));
        const float m = h ? m1 : m0;
        return pack2(fmaf(-m, c0, acc[4 * j + 2 * h]), fmaf(-m, c1, acc[4 * j + 2 * h + 1]));
    };
#pragma unroll
    for (int f = 0; f < 10; f++) { kh[f] = fold(1, f, 1); vh[f] = fold(2, f, 1); }
    if (w == 3) {
        uint4* hp = &g_halo[bx][wg][0][lane];
        st_ll4(hp, (kh[0] & ~1u) | ob, kh[1], kh[3], kh[4]); st_ll4(hp + 32, (kh[5] & ~1u) | ob, kh[6], kh[8], kh[9]);
        st_ll4(hp + 64, (vh[0] & ~1u) | ob, vh[1], vh[2], vh[3]); st_ll4(hp + 96, (vh[4] & ~1u) | ob, vh[5], vh[6], vh[7]);
        st_ll4(hp + 128, (vh[8] & ~1u) | ob, vh[9], kh[2], kh[7]);
    } else {
        const uint32_t a = sb + Q_EOFF + wg * 8192 + w * Q_ESLOT + mj * Q_EROW + mi * 16;
        stsm_x4(a, kh[0], kh[1], kh[3], kh[4]);
        stsm_x4(a + 64, kh[5], kh[6], kh[8], kh[9]);
        stsm_x4(a + 128, vh[0], vh[1], vh[2], vh[3]);
        stsm_x4(a + 192, vh[4], vh[5], vh[6], vh[7]);
        stsm_x4(a + 256, vh[8], vh[9], kh[2], kh[7]);
        __syncwarp();
        if (lane == 0) mbar_arrive(BAR(ex) + 8 * warp);
    }
    TS(9);
    cs_load(0);
#pragma unroll
    for (int f = 0; f < 10; f++) { kl[f] = fold(1, f, 0); vl[f] = fold(2, f, 0); }
#pragma unroll
    for (int f = 0; f < 10; f++) { ql[f] = fold(0, f, 0); qh[f] = fold(0, f, 1); }
    auto rs = [&](int i) { return __uint_as_float(lds32(s2u(&s_rstd[wg][16 * w + i]))); };
    const float kx0 = rs(2 * q + (sel0 ? 0 : 8)), kx1 = rs(2 * q + (sel1 ? 1 : 9)), ky0 = rs(2 * q + (sel0 ? 8 : 16)), ky1 = rs(2 * q + (sel1 ? 9 : 17));
    const float rx = SC * rs(8 + g), ry = SC * rs(16 + g), cx0 = rx * kx0, cx1 = rx * kx1, cy0 = ry * ky0, cy1 = ry * ky1;
    uint4 hv[5];
    const uint4* hp = &g_halo[bx - 1][wg][0][lane];
    auto prev = [&] {
        if (w > 0) {
            const uint32_t a = sb + Q_EOFF + wg * 8192 + (w - 1) * Q_ESLOT + mj * Q_EROW + mi * 16;
            mbar_wait(BAR(ex) + 8 * (warp - 1), 0);
            ldsm_x4(hv[0].x, hv[0].y, hv[0].z, hv[0].w, a);
            ldsm_x4(hv[1].x, hv[1].y, hv[1].z, hv[1].w, a + 64);
            ldsm_x4_t(hv[2].x, hv[2].y, hv[2].z, hv[2].w, a + 128);
            ldsm_x4_t(hv[3].x, hv[3].y, hv[3].z, hv[3].w, a + 192);
            ldsm_x2_t(hv[4].x, hv[4].y, a + 256);
            ldsm_x2(hv[4].z, hv[4].w, a + 288 - (lane >> 4) * 32);
        } else if (blk > 0) {
#pragma unroll
            for (int f = 0; f < 5; f++) hv[f] = ld_ll4(hp + 32 * f);
        } else {
#pragma unroll
            for (int f = 0; f < 5; f++) hv[f] = make_uint4(0, 0, 0, 0);
        }
    };
    if (A_HPOS == 0) prev();
    uint32_t vt[10][2];
#pragma unroll
    for (int f = 0; f < 10; f++) { vt[f][0] = movm_t(vl[f]); vt[f][1] = movm_t(vh[f]); }
    if (A_HPOS == 1) prev();
    TS(10);
    auto FA = [](int h) { return h == 0 ? 0 : h == 1 ? 3 : h == 2 ? 5 : 8; };
    auto FH = [](int h) { return h < 2 ? 2 : 7; };
    const uint32_t pm = (sel0 ? 0xFFFFu : 0u) | (sel1 ? 0xFFFF0000u : 0u);
    auto softmax = [&](float x0, float x1, float k0, float k1) {
        float mx = fmaxf(x0, x1);
        mx = fmaxf(mx, __shfl_xor_sync(~0u, mx, 1));
        mx = fmaxf(mx, __shfl_xor_sync(~0u, mx, 2));
        x0 = ex2(x0 - mx); x1 = ex2(x1 - mx);
        float sx = x0 + x1;
        sx += __shfl_xor_sync(~0u, sx, 1);
        sx += __shfl_xor_sync(~0u, sx, 2);
        const float ix = frcp(sx);
        return pack2(x0 * k0 * ix, x1 * k1 * ix);
    };
    uint32_t qm[4][2], py[4];
    float sl[4][2];
#pragma unroll
    for (int h = 0; h < 4; h++) {
        const int fa = FA(h), fb = fa + 1, fh = FH(h);
        const bool mine = (h & 1) ? (q >= 2) : (q < 2);
        qm[h][0] = mine ? ql[fh] : 0u; qm[h][1] = mine ? qh[fh] : 0u;
        float S1[4] = {0.f, 0.f, 0.f, 0.f}, S2[4] = {0.f, 0.f, 0.f, 0.f};
        mma16816(S1, ql[fa], qh[fa], ql[fb], qh[fb], kl[fa], kl[fb]); mma1688(S1, qm[h][0], qm[h][1], kl[fh]);
        mma16816(S2, ql[fa], qh[fa], ql[fb], qh[fb], kh[fa], kh[fb]); mma1688(S2, qm[h][0], qm[h][1], kh[fh]);
        sl[h][0] = S1[0]; sl[h][1] = S1[1];
        py[h] = softmax((sel0 ? S1[2] : S2[2]) * cy0, (sel1 ? S1[3] : S2[3]) * cy1, ky0, ky1);
    }
    TS(11);
    if (w == 0 && blk > 0) {
        int spin = 0;
        while (__any_sync(~0u, ((hv[0].x ^ ob) | (hv[1].x ^ ob) | (hv[2].x ^ ob) | (hv[3].x ^ ob) | (hv[4].x ^ ob)) & 1u) && ++spin < (1 << 18)) {
#pragma unroll
            for (int f = 0; f < 5; f++) hv[f] = ld_ll4(hp + 32 * f);
        }
#pragma unroll
        for (int f = 2; f < 4; f++) hv[f] = make_uint4(movm_t(hv[f].x), movm_t(hv[f].y), movm_t(hv[f].z), movm_t(hv[f].w));
        hv[4].x = movm_t(hv[4].x); hv[4].y = movm_t(hv[4].y);
    }
    const uint32_t kp[10] = {hv[0].x, hv[0].y, hv[4].z, hv[0].z, hv[0].w, hv[1].x, hv[1].y, hv[4].w, hv[1].z, hv[1].w};
    const uint32_t vp[10] = {hv[2].x, hv[2].y, hv[2].z, hv[2].w, hv[3].x, hv[3].y, hv[3].z, hv[3].w, hv[4].x, hv[4].y};
    TS(12);
    const uint4 ko[2] = {ldg_tab(16, tid & 127), ldg_tab(17, tid & 127)};
    const float bx0 = first && sel0 ? -INFINITY : 0.f, bx1 = first && sel1 ? -INFINITY : 0.f;
    float oacc[10][4];
#pragma unroll
    for (int h = 0; h < 4; h++) {
        const int fa = FA(h), fb = fa + 1, fh = FH(h);
        const bool mine = (h & 1) ? (q >= 2) : (q < 2);
        float S0[4] = {0.f, 0.f, 0.f, 0.f};
        mma16816(S0, ql[fa], qh[fa], ql[fb], qh[fb], kp[fa], kp[fb]); mma1688(S0, qm[h][0], qm[h][1], kp[fh]);
        const uint32_t px = softmax(fmaf(sel0 ? S0[0] : sl[h][0], cx0, bx0), fmaf(sel1 ? S0[1] : sl[h][1], cx1, bx1), kx0, kx1);
#pragma unroll
        for (int i = 0; i < 3; i++) {
            const int f = (i == 0) ? fa : (i == 1) ? fb : fh;
            float O[4] = {0.f, 0.f, 0.f, 0.f};
            mma16816(O, px & ~pm, py[h] & pm, 0u, py[h] & ~pm, vt[f][0], vt[f][1]);
            mma1688(O, px & pm, 0u, vp[f]);
            if (i < 2 || !(h & 1) || mine) { oacc[f][0] = O[0]; oacc[f][1] = O[1]; oacc[f][2] = O[2]; oacc[f][3] = O[3]; }
        }
    }
    TS(13);
    constexpr int ON = O_DEPTH + 2;
    uint4 of[ON][5];
    {
        uint4* dst = &g_of[hg][blk][warp][0][lane];
#pragma unroll
        for (int k = 0; k < 5; k++) {
            of[0][k] = make_uint4((pack2(oacc[2 * k][0], oacc[2 * k][1]) & ~1u) | ob, pack2(oacc[2 * k][2], oacc[2 * k][3]),
                                  pack2(oacc[2 * k + 1][0], oacc[2 * k + 1][1]), pack2(oacc[2 * k + 1][2], oacc[2 * k + 1][3]));
            st_ll4(dst + 32 * k, of[0][k].x, of[0][k].y, of[0][k].z, of[0][k].w);
        }
    }
    if (wg == 1 && lane == 0) mbar_arrive(BAR(att1));
    TS(14);
    float aw[40];
    auto omma = [&](int j) {
        const uint64_t dm = mkdesc(sb + w_grp(j), 1280, 128, 0);
        wg_fence();
#pragma unroll
        for (int k = 0; k < 5; k++) wgmma_rs80(aw, of[j % ON][k], dm + k * 160, j + k > 0);
        wg_commit();
    };
    mbar_wait(BAR(wfull), 0);
    omma(0);
    named_bar(1 + wg, 128);
    kernel_stage<2>(ko, sb + Q_KDUMP + 2 * wg * KG_RES, sb + F_EO + wg * 8192, w, lane);
    TS(8);
    const uint4* osrc = &g_of[0][blk][warp][0][lane];
    auto oload = [&](int j) {
        const uint4* p = osrc + osrc_of(j) * 20480;
#pragma unroll
        for (int k = 0; k < 5; k++) of[j % ON][k] = ld_ll4(p + 32 * k);
    };
    {
        const uint32_t* pp = &g_of[osrc_of(1 + min(lane, 6))][blk][warp][4][31].x;
        uint32_t v;
        int spin = 0;
        do { asm volatile("ld.relaxed.gpu.global.u32 %0, [%1];" : "=r"(v) : "l"(pp) : "memory"); } while (__any_sync(~0u, (v & 1u) != ob) && ++spin < (1 << 18));
    }
    TS(15);
    if (O_PASS && wg == 1) mbar_wait(BAR(pass), 0);
#pragma unroll
    for (int j = 1; j <= O_DEPTH; j++) oload(j);
    TS(16);
#pragma unroll
    for (int j = 1; j < 8; j++) {
        if (j == 3 || j == 7) mbar_wait(BAR(wfull) + 8 * ((j + 1) >> 2), 0);
        const uint4* f = of[j % ON];
        int spin = 0;
        while (__any_sync(~0u, ((f[0].x ^ ob) | (f[1].x ^ ob) | (f[2].x ^ ob) | (f[3].x ^ ob) | (f[4].x ^ ob)) & 1u) && ++spin < (1 << 18)) oload(j);
        if (j + O_DEPTH < 8) { wg_wait<1>(); oload(j + O_DEPTH); }
        if (j == O_PASS && wg == 0 && lane == 0) mbar_arrive(BAR(pass));
        if (j == O_TPOS) { wg_wait<1>(); conv_tables(); }
        if (j == 1) TS(17);
        if (j == 5) TS(18);
        omma(j);
    }
    wg_wait<2>();
    uint32_t res[20];
    mbar_wait(BAR(res), 0);
    const uint32_t ta = (8 * (mi >> 1) + mj) * 128 + (((2 * w + (mi & 1)) ^ mj) << 4);
    if (layer == 0) {
        const int tok = 16 * w + 8 * (mi & 1) + mj;
#pragma unroll
        for (int k = 0; k < 4; k++)
            ldsm_x4(res[4 * k], res[4 * k + 1], res[4 * k + 2], res[4 * k + 3], sb + W_RES + wg * 10240 + tok * 128 + (((2 * k + (mi >> 1)) ^ mj) << 4));
        ldsm_x4(res[16], res[17], res[18], res[19], sb + W_RES + wg * 10240 + 8192 + tok * 32 + (((mi >> 1) ^ (mj >> 2)) << 4));
    } else {
#pragma unroll
        for (int k = 0; k < 5; k++) ldsm_x4_t(res[4 * k], res[4 * k + 1], res[4 * k + 2], res[4 * k + 3], sb + W_RES + wg * 10240 + k * 2048 + ta);
    }
    named_bar(1 + wg, 128);
    wg_wait<0>();
    TS(19);
#pragma unroll
    for (int i = 0; i < 20; i++) {
        const uint32_t y = pack2(aw[2 * i], aw[2 * i + 1]);
        asm("add.rn.bf16x2 %0, %0, %1;" : "+r"(res[i]) : "r"(y));
    }
#pragma unroll
    for (int k = 0; k < 5; k++) stsm_x4_t(sb + W_RES + wg * 10240 + k * 2048 + ta, res[4 * k], res[4 * k + 1], res[4 * k + 2], res[4 * k + 3]);
    fence_async_smem();
    __syncwarp();
    if (lane == 0) mbar_arrive(BAR(staged) + 8 * wg);
    TS(20);
    {
        float sm[4] = {0.f, 0.f, 0.f, 0.f}, d0[4] = {0.f, 0.f, 0.f, 0.f}, d1[4] = {0.f, 0.f, 0.f, 0.f};
#pragma unroll
        for (int k = 0; k < 5; k++) {
            mma16816(sm, res[4 * k], res[4 * k + 1], res[4 * k + 2], res[4 * k + 3], 0x3F803F80u, 0x3F803F80u);
            mma16816(d0, res[4 * k], res[4 * k + 1], res[4 * k + 2], res[4 * k + 3], res[4 * k], res[4 * k + 2]);
            mma16816(d1, res[4 * k], res[4 * k + 1], res[4 * k + 2], res[4 * k + 3], res[4 * k + 1], res[4 * k + 3]);
        }
        if (q == (g >> 1))
            st_ll4(&g_sp2[blk][warp][hg][g], (__float_as_uint(sm[0]) & ~1u) | ob, __float_as_uint((g & 1) ? d0[1] : d0[0]), __float_as_uint(sm[2]),
                   __float_as_uint((g & 1) ? d1[3] : d1[2]));
    }
    if (O_TPOS == 9) conv_tables();
    TS(21);
    named_bar(1 + wg, 128);
    TS(22);
    TS_PHASE(2 * layer + 1);
    TS(0);
    indices();
    conv_wg<2>(5 * bx + 2 * (warp >> 2), layer, sb + F_EO + (warp >> 2) * 8192, sb + (warp >> 2) * Q_SB, sb + F_S23, s2u(&s_kg.kexp[2 * (warp >> 2)]),
               sb + 3 * Q_SB, BAR(st), warp, lane, fa1, ftw, [] {}, [&] {
        if (warp == 0) {
            grid_wait(g_bar[layer][0], 8, 32 * (EPOCH + 1), lane);
            if (lane == 0) mbar_arrive(BAR(ardy));
        } else {
            mbar_wait(BAR(ardy), 0);
        }
    }, [] {} TS_PASS);
    conv_done();
    asm volatile("setmaxnreg.dec.sync.aligned.u32 168;");
    }
    named_bar(1 + (warp >> 2), 128);
    asm volatile("setmaxnreg.dec.sync.aligned.u32 %0;" ::"n"(504 - 2 * R_CONS));
    }
    indices();
    __syncthreads();
    if (FIN_DELAY) { const long long t0 = clock64(); while (clock64() - t0 < FIN_DELAY) {} }
    if (tid < 320) {
        const int p = warp & 1, cq = 4 * (warp >> 1) + (lane >> 3), tg = lane & 7;
        const uint4* src = (const uint4*)(g_x2T[1] + (size_t)(80 * hg + 4 * cq) * XP + 1024 * p + 64 * blk + 8 * tg);
        uint4 v[4];
#pragma unroll
        for (int i = 0; i < 4; i++) v[i] = make_uint4(0, 0, 0, 0);
        int spin = 0;
        while (true) {
            bool ok = true;
#pragma unroll
            for (int i = 0; i < 4; i++) if (v[i].x == 0u || v[i].z == 0u) v[i] = ld_ll4(src + i * (XP / 8));
#pragma unroll
            for (int i = 0; i < 4; i++) ok = ok && v[i].x != 0u && v[i].z != 0u;
            if (ok || ++spin >= (1 << 18)) break;
            if (FIN_SLEEP) __nanosleep(FIN_SLEEP);
        }
        TS(21);
#pragma unroll
        for (int i = 0; i < 8; i++) {
            const uint32_t sel = (i & 1) ? 0x7632 : 0x5410;
            asm volatile("st.shared.v2.u32 [%0], {%1, %2};" ::"r"(sb + (8 * (2 * i + p) + tg) * 160 + cq * 8),
                         "r"(__byte_perm(u4(v[0], i >> 1), u4(v[1], i >> 1), sel)), "r"(__byte_perm(u4(v[2], i >> 1), u4(v[3], i >> 1), sel)) : "memory");
        }
        fence_async_smem();
    }
    __syncthreads();
    if (warp == 0 && elect_one()) {
        asm volatile("cp.async.bulk.tensor.3d.global.shared::cta.bulk_group [%0, {%2, %3, 0}], [%1];" ::"l"(TMAP(9)), "r"(sb), "r"(80 * hg), "r"(8 * blk) : "memory");
        bulk_commit();
        asm volatile("cp.async.bulk.wait_group.read 0;" ::: "memory");
    }
    if (bx == 0 && tid == 0) g_epoch = EPOCH + 1;
    TS(22);
    TS_END;
}
typedef CUresult (*EncodeTiledFn)(CUtensorMap*, CUtensorMapDataType, cuuint32_t, void*, const cuuint64_t*, const cuuint64_t*, const cuuint32_t*,
                                  const cuuint32_t*, CUtensorMapInterleave, CUtensorMapSwizzle, CUtensorMapL2promotion, CUtensorMapFloatOOBfill);

static void make_map(EncodeTiledFn enc, CUtensorMap* m, const void* base, int rank, const cuuint64_t* dims, const cuuint64_t* strides,
                     const cuuint32_t* box, CUtensorMapSwizzle sw) {
    cuuint32_t es[4] = {1, 1, 1, 1};
    enc(m, CU_TENSOR_MAP_DATA_TYPE_BFLOAT16, rank, (void*)base, dims, strides, box, es, CU_TENSOR_MAP_INTERLEAVE_NONE, sw,
        sw == CU_TENSOR_MAP_SWIZZLE_128B ? CU_TENSOR_MAP_L2_PROMOTION_L2_128B : CU_TENSOR_MAP_L2_PROMOTION_NONE, CU_TENSOR_MAP_FLOAT_OOB_FILL_NONE);
}

template <typename... KArgs, typename... Args>
static void launch(void (*kern)(KArgs...), int grid, int block, int smem, int cluster, bool pdl, Args... args) {
    cudaLaunchConfig_t cfg = {};
    cfg.gridDim = dim3(grid); cfg.blockDim = dim3(block); cfg.dynamicSmemBytes = smem; cfg.stream = cudaStreamPerThread;
    cudaLaunchAttribute at[2];
    int n = 0;
    if (cluster > 1) { at[n].id = cudaLaunchAttributeClusterDimension; at[n].val.clusterDim.x = cluster; at[n].val.clusterDim.y = 1; at[n].val.clusterDim.z = 1; n++; }
    if (pdl) { at[n].id = cudaLaunchAttributeProgrammaticStreamSerialization; at[n].val.programmaticStreamSerializationAllowed = 1; n++; }
    cfg.attrs = at; cfg.numAttrs = n;
    cudaLaunchKernelEx(&cfg, kern, KArgs(args)...);
}

struct HostState {
    bool ready = false;
    const void* key[4] = {nullptr, nullptr, nullptr, nullptr};
    CUtensorMap mX[2], mRes[2], mW, mWr, mWo, mOut, mFin, mResA;
    bf16 *x1T, *x2T;
};

extern "C" void kernel_launch(void* const* d_in, const int* in_sizes, int n_in, void* d_out, int out_size) {
    const bf16* x = (const bf16*)d_in[0];
    const bf16* wqkv = (const bf16*)d_in[1];
    const bf16* wo = (const bf16*)d_in[2];
    const bf16* lar = (const bf16*)d_in[4];
    const bf16* aim = (const bf16*)d_in[5];
    const bf16* cre = (const bf16*)d_in[6];
    const bf16* cim = (const bf16*)d_in[7];
    const bf16* logdt = (const bf16*)d_in[8];
    const bf16* dskip = (const bf16*)d_in[9];
    static HostState hs;
    if (!hs.ready || hs.key[0] != wqkv || hs.key[1] != wo || hs.key[2] != x || hs.key[3] != d_out) {
        void* fn = nullptr;
        cudaDriverEntryPointQueryResult qr;
        cudaGetDriverEntryPoint("cuTensorMapEncodeTiled", &fn, cudaEnableDefault, &qr);
        EncodeTiledFn enc = (EncodeTiledFn)fn;
        cudaGetSymbolAddress((void**)&hs.x1T, g_x1T);
        cudaGetSymbolAddress((void**)&hs.x2T, g_x2T);
        {
            cuuint64_t d[3] = {DM, SEQ / 2, 2}, s[2] = {DM * 4, DM * 2};
            cuuint32_t b[3] = {64, 64, 2}, ba[3] = {64, 64, 1}, br[3] = {16, 64, 1};
            make_map(enc, &hs.mX[0], x, 3, d, s, b, CU_TENSOR_MAP_SWIZZLE_128B);
            make_map(enc, &hs.mResA, x, 3, d, s, ba, CU_TENSOR_MAP_SWIZZLE_128B);
            make_map(enc, &hs.mRes[0], x, 3, d, s, br, CU_TENSOR_MAP_SWIZZLE_32B);
            cuuint64_t d2[3] = {SEQ / 2, DM, 2}, s2[2] = {XP * 2, SEQ};
            cuuint32_t b2[3] = {64, 80, 2};
            make_map(enc, &hs.mX[1], hs.x2T, 3, d2, s2, b, CU_TENSOR_MAP_SWIZZLE_128B);
            make_map(enc, &hs.mRes[1], hs.x2T, 3, d2, s2, b2, CU_TENSOR_MAP_SWIZZLE_128B);
            cuuint64_t d3[2] = {SEQ, DM};
            make_map(enc, &hs.mOut, hs.x1T, 2, d3, s2, b2, CU_TENSOR_MAP_SWIZZLE_128B);
        }
        { cuuint64_t d[2] = {3 * DM, DM}, s[1] = {3 * DM * 2}; cuuint32_t b[2] = {64, 32};
          make_map(enc, &hs.mW, wqkv, 2, d, s, b, CU_TENSOR_MAP_SWIZZLE_128B); }
        { cuuint64_t d[3] = {DM, DM, 3}, s[2] = {3 * DM * 2, DM * 2}; cuuint32_t b[3] = {16, 32, 3};
          make_map(enc, &hs.mWr, wqkv, 3, d, s, b, CU_TENSOR_MAP_SWIZZLE_32B); }
        { cuuint64_t d[4] = {8, 8, DM / 8, DM / 8}, s[3] = {DM * 2, 16, DM * 16}; cuuint32_t b[4] = {8, 8, 10, 5};
          make_map(enc, &hs.mWo, wo, 4, d, s, b, CU_TENSOR_MAP_SWIZZLE_NONE); }
        { cuuint64_t d[3] = {DM, SEQ / 16, 16}, s[2] = {DM * 32, DM * 2}; cuuint32_t b[3] = {80, 8, 16};
          make_map(enc, &hs.mFin, d_out, 3, d, s, b, CU_TENSOR_MAP_SWIZZLE_NONE); }
        cudaFuncSetAttribute(fused_kernel, cudaFuncAttributeMaxDynamicSharedMemorySize, Q_SMEM);
        hs.key[0] = wqkv; hs.key[1] = wo; hs.key[2] = x; hs.key[3] = d_out;
        hs.ready = true;
    }
    const SsmParams sp = {lar, aim, cre, cim, logdt, dskip};
    launch(fused_kernel, 128, 384, Q_SMEM, 2, false, sp, hs.mX[0], hs.mX[1], hs.mW, hs.mWr, hs.mRes[0], hs.mRes[1], hs.mOut, hs.mWo, hs.mFin, hs.mResA);
}
```

```cpp
#include <cuda_runtime.h>
#include <cuda.h>
#include <cuda_bf16.h>
#include <cuda_fp16.h>
#include <stdint.h>

typedef __nv_bfloat16 bf16;

constexpr int SEQ = 2048;
constexpr int DM  = 640;
constexpr int XP  = SEQ + 64;
constexpr int NMODE = 192;

__device__ __forceinline__ uint32_t s2u(const void* p) { return (uint32_t)__cvta_generic_to_shared(p); }
__device__ __forceinline__ void mbar_init(uint32_t b, int c) { asm volatile("mbarrier.init.shared::cta.b64 [%0], %1;" ::"r"(b), "r"(c)); }
__device__ __forceinline__ void mbar_expect(uint32_t b, uint32_t bytes) { asm volatile("mbarrier.arrive.expect_tx.shared::cta.b64 _, [%0], %1;" ::"r"(b), "r"(bytes) : "memory"); }
__device__ __forceinline__ void mbar_arrive(uint32_t b) { asm volatile("mbarrier.arrive.shared::cta.b64 _, [%0];" ::"r"(b) : "memory"); }
__device__ __forceinline__ void mbar_arrive_cta(uint32_t b, uint32_t cta) {
    asm volatile("{\n.reg .b32 ra;\nmapa.shared::cluster.u32 ra, %0, %1;\nmbarrier.arrive.shared::cluster.b64 _, [ra];\n}" ::"r"(b), "r"(cta) : "memory");
}
__device__ __forceinline__ void mbar_wait(uint32_t b, uint32_t ph) {
#ifdef M_PLAIN
    asm volatile("{\n.reg .pred p;\nW: mbarrier.try_wait.parity.shared::cta.b64 p, [%0], %1;\n@!p bra W;\n}" ::"r"(b), "r"(ph) : "memory");
    return;
#endif
    asm volatile("{\n.reg .pred p;\n.reg .u32 n;\nmbarrier.try_wait.parity.shared::cta.b64 p, [%0], %1;\n@p bra D;\nmov.u32 n, 0;\n"
                 "W: mbarrier.try_wait.parity.shared::cta.b64 p, [%0], %1;\n@p bra D;\nadd.u32 n, n, 1;\nsetp.lt.u32 p, n, 4194304;\n@p bra W;\ntrap;\nD:\n}"
                 ::"r"(b), "r"(ph) : "memory");
}
__device__ __forceinline__ void fence_mbar_init() { asm volatile("fence.mbarrier_init.release.cluster;" ::: "memory"); }
__device__ __forceinline__ void cluster_sync() { asm volatile("barrier.cluster.arrive.aligned;\nbarrier.cluster.wait.aligned;" ::: "memory"); }
__device__ __forceinline__ void pdl_wait() { asm volatile("griddepcontrol.wait;" ::: "memory"); }
__device__ __forceinline__ void pdl_launch() { asm volatile("griddepcontrol.launch_dependents;" ::: "memory"); }
__device__ __forceinline__ void named_bar(int id, int n) { asm volatile("bar.sync %0, %1;" ::"r"(id), "r"(n) : "memory"); }
__device__ __forceinline__ void fence_async_smem() { asm volatile("fence.proxy.async.shared::cta;" ::: "memory"); }

__device__ __forceinline__ void tma2d(uint32_t dst, const CUtensorMap* m, int c0, int c1, uint32_t bar) {
    asm volatile("cp.async.bulk.tensor.2d.shared::cluster.global.mbarrier::complete_tx::bytes [%0], [%1, {%3, %4}], [%2];"
                 ::"r"(dst), "l"(m), "r"(bar), "r"(c0), "r"(c1) : "memory");
}
__device__ __forceinline__ void tma2d_mc(uint32_t dst, const CUtensorMap* m, int c0, int c1, uint32_t bar, uint16_t mask) {
    asm volatile("cp.async.bulk.tensor.2d.shared::cluster.global.mbarrier::complete_tx::bytes.multicast::cluster [%0], [%1, {%3, %4}], [%2], %5;"
                 ::"r"(dst), "l"(m), "r"(bar), "r"(c0), "r"(c1), "h"(mask) : "memory");
}
__device__ __forceinline__ void tma3d(uint32_t dst, const CUtensorMap* m, int c0, int c1, int c2, uint32_t bar) {
    asm volatile("cp.async.bulk.tensor.3d.shared::cluster.global.mbarrier::complete_tx::bytes [%0], [%1, {%3, %4, %5}], [%2];"
                 ::"r"(dst), "l"(m), "r"(bar), "r"(c0), "r"(c1), "r"(c2) : "memory");
}
__device__ __forceinline__ void tma3d_mc(uint32_t dst, const CUtensorMap* m, int c0, int c1, int c2, uint32_t bar, uint16_t mask) {
    asm volatile("cp.async.bulk.tensor.3d.shared::cluster.global.mbarrier::complete_tx::bytes.multicast::cluster [%0], [%1, {%3, %4, %5}], [%2], %6;"
                 ::"r"(dst), "l"(m), "r"(bar), "r"(c0), "r"(c1), "r"(c2), "h"(mask) : "memory");
}
__device__ __forceinline__ void bulk_g2s(uint32_t dst, const void* src, uint32_t bytes, uint32_t bar) {
    asm volatile("cp.async.bulk.shared::cluster.global.mbarrier::complete_tx::bytes [%0], [%1], %2, [%3];"
                 ::"r"(dst), "l"(src), "r"(bytes), "r"(bar) : "memory");
}
__device__ __forceinline__ void bulk_g2s_mc(uint32_t dst, const void* src, uint32_t bytes, uint32_t bar, uint16_t mask) {
    asm volatile("cp.async.bulk.shared::cluster.global.mbarrier::complete_tx::bytes.multicast::cluster [%0], [%1], %2, [%3], %4;"
                 ::"r"(dst), "l"(src), "r"(bytes), "r"(bar), "h"(mask) : "memory");
}
__device__ __forceinline__ void prefetch_l2(const void* p, uint32_t bytes) { asm volatile("cp.async.bulk.prefetch.L2.global [%0], %1;" ::"l"(p), "r"(bytes) : "memory"); }
__device__ __forceinline__ void prefetch_tmap(const CUtensorMap* m) { asm volatile("prefetch.tensormap [%0];" ::"l"(m) : "memory"); }

__device__ __forceinline__ void wg_fence() { asm volatile("wgmma.fence.sync.aligned;" ::: "memory"); }
__device__ __forceinline__ void wg_commit() { asm volatile("wgmma.commit_group.sync.aligned;" ::: "memory"); }
template <int N> __device__ __forceinline__ void wg_wait() { asm volatile("wgmma.wait_group.sync.aligned %0;" ::"n"(N) : "memory"); }
__device__ __forceinline__ uint64_t mkdesc(uint32_t addr, uint32_t lbo, uint32_t sbo, uint32_t mode) {
    return (uint64_t)((addr & 0x3FFFF) >> 4) | ((uint64_t)(lbo >> 4) << 16) | ((uint64_t)(sbo >> 4) << 32) | ((uint64_t)mode << 62);
}

__device__ __forceinline__ void mma16816(float (&c)[4], uint32_t a0, uint32_t a1, uint32_t a2, uint32_t a3, uint32_t b0, uint32_t b1) {
    asm("mma.sync.aligned.m16n8k16.row.col.f32.bf16.bf16.f32 {%0,%1,%2,%3},{%4,%5,%6,%7},{%8,%9},{%0,%1,%2,%3};"
                 : "+f"(c[0]), "+f"(c[1]), "+f"(c[2]), "+f"(c[3]) : "r"(a0), "r"(a1), "r"(a2), "r"(a3), "r"(b0), "r"(b1));
}
__device__ __forceinline__ void mma1688(float (&c)[4], uint32_t a0, uint32_t a1, uint32_t b0) {
    asm("mma.sync.aligned.m16n8k8.row.col.f32.bf16.bf16.f32 {%0,%1,%2,%3},{%4,%5},{%6},{%0,%1,%2,%3};"
                 : "+f"(c[0]), "+f"(c[1]), "+f"(c[2]), "+f"(c[3]) : "r"(a0), "r"(a1), "r"(b0));
}
__device__ __forceinline__ void ldsm_x4(uint32_t& r0, uint32_t& r1, uint32_t& r2, uint32_t& r3, uint32_t a) {
    asm volatile("ldmatrix.sync.aligned.m8n8.x4.shared.b16 {%0,%1,%2,%3}, [%4];" : "=r"(r0), "=r"(r1), "=r"(r2), "=r"(r3) : "r"(a) : "memory");
}
__device__ __forceinline__ void ldsm_x4_t(uint32_t& r0, uint32_t& r1, uint32_t& r2, uint32_t& r3, uint32_t a) {
    asm volatile("ldmatrix.sync.aligned.m8n8.x4.trans.shared.b16 {%0,%1,%2,%3}, [%4];" : "=r"(r0), "=r"(r1), "=r"(r2), "=r"(r3) : "r"(a) : "memory");
}
__device__ __forceinline__ void ldsm_x2(uint32_t& r0, uint32_t& r1, uint32_t a) {
    asm volatile("ldmatrix.sync.aligned.m8n8.x2.shared.b16 {%0,%1}, [%2];" : "=r"(r0), "=r"(r1) : "r"(a) : "memory");
}
__device__ __forceinline__ void ldsm_x2_t(uint32_t& r0, uint32_t& r1, uint32_t a) {
    asm volatile("ldmatrix.sync.aligned.m8n8.x2.trans.shared.b16 {%0,%1}, [%2];" : "=r"(r0), "=r"(r1) : "r"(a) : "memory");
}
__device__ __forceinline__ void stsm_x4(uint32_t a, uint32_t r0, uint32_t r1, uint32_t r2, uint32_t r3) {
    asm volatile("stmatrix.sync.aligned.m8n8.x4.shared.b16 [%0], {%1,%2,%3,%4};" ::"r"(a), "r"(r0), "r"(r1), "r"(r2), "r"(r3) : "memory");
}
__device__ __forceinline__ void stsm_x4_t(uint32_t a, uint32_t r0, uint32_t r1, uint32_t r2, uint32_t r3) {
    asm volatile("stmatrix.sync.aligned.m8n8.x4.trans.shared.b16 [%0], {%1,%2,%3,%4};" ::"r"(a), "r"(r0), "r"(r1), "r"(r2), "r"(r3) : "memory");
}
__device__ __forceinline__ void stsm_x2(uint32_t a, uint32_t r0, uint32_t r1) {
    asm volatile("stmatrix.sync.aligned.m8n8.x2.shared.b16 [%0], {%1,%2};" ::"r"(a), "r"(r0), "r"(r1) : "memory");
}
__device__ __forceinline__ uint32_t movm_t(uint32_t a) {
    uint32_t d;
    asm volatile("movmatrix.sync.aligned.m8n8.trans.b16 %0, %1;" : "=r"(d) : "r"(a));
    return d;
}
__device__ __forceinline__ uint32_t lds32(uint32_t a) { uint32_t v; asm volatile("ld.shared.u32 %0, [%1];" : "=r"(v) : "r"(a) : "memory"); return v; }
__device__ __forceinline__ uint32_t ldsv32(uint32_t a) { uint32_t v; asm volatile("ld.volatile.shared.u32 %0, [%1];" : "=r"(v) : "r"(a) : "memory"); return v; }
__device__ __forceinline__ void sts32(uint32_t a, uint32_t v) { asm volatile("st.shared.u32 [%0], %1;" ::"r"(a), "r"(v) : "memory"); }
__device__ __forceinline__ uint4 lds128(uint32_t a) { uint4 v; asm volatile("ld.shared.v4.u32 {%0,%1,%2,%3}, [%4];" : "=r"(v.x), "=r"(v.y), "=r"(v.z), "=r"(v.w) : "r"(a) : "memory"); return v; }
__device__ __forceinline__ void sts128(uint32_t a, uint4 v) { asm volatile("st.shared.v4.u32 [%0], {%1,%2,%3,%4};" ::"r"(a), "r"(v.x), "r"(v.y), "r"(v.z), "r"(v.w) : "memory"); }

__device__ __forceinline__ void stg128(void* p, uint4 v) { asm volatile("st.global.v4.u32 [%0], {%1,%2,%3,%4};" ::"l"(p), "r"(v.x), "r"(v.y), "r"(v.z), "r"(v.w) : "memory"); }

__device__ __forceinline__ uint4 ldg128(const void* p) { uint4 v; asm volatile("ld.global.v4.u32 {%0,%1,%2,%3}, [%4];" : "=r"(v.x), "=r"(v.y), "=r"(v.z), "=r"(v.w) : "l"(p) : "memory"); return v; }
__device__ __forceinline__ uint2 ldg64(const void* p) { uint2 v; asm volatile("ld.global.v2.u32 {%0,%1}, [%2];" : "=r"(v.x), "=r"(v.y) : "l"(p) : "memory"); return v; }
__device__ __forceinline__ uint32_t ldg32(const void* p) { uint32_t v; asm volatile("ld.global.u32 %0, [%1];" : "=r"(v) : "l"(p) : "memory"); return v; }

__device__ __forceinline__ uint32_t pack2(float lo, float hi) {
    uint32_t r;
    asm("cvt.rn.bf16x2.f32 %0, %1, %2;" : "=r"(r) : "f"(hi), "f"(lo));
    return r;
}
__device__ __forceinline__ float bf_lo(uint32_t v) { return __uint_as_float(v << 16); }
__device__ __forceinline__ float bf_hi(uint32_t v) { return __uint_as_float(v & 0xFFFF0000u); }
__device__ __forceinline__ float rbf(float x) { return __uint_as_float(pack2(0.f, x) & 0xFFFF0000u); }
__device__ __forceinline__ float ex2(float x) { float r; asm("ex2.approx.ftz.f32 %0, %1;" : "=f"(r) : "f"(x)); return r; }

__device__ __forceinline__ float2 ln_finish(float sum, float sumsq) {
    const float m = sum * (1.0f / DM);
    const float v = fmaxf(fmaf(sumsq, 1.0f / DM, -m * m), 0.f);
    float s, r;
    asm("sqrt.approx.ftz.f32 %0, %1;" : "=f"(s) : "f"(rbf(rbf(v) + 1e-5f)));
    asm("rcp.approx.ftz.f32 %0, %1;" : "=f"(r) : "f"(rbf(s)));
    return make_float2(m, r);
}
__device__ __forceinline__ uint32_t ln_finish_packed(float sum, float sumsq) {
    const float m = sum * (1.0f / DM);
    const float v = fmaxf(fmaf(sumsq, 1.0f / DM, -m * m), 0.f);
    float s;
    asm("sqrt.approx.ftz.f32 %0, %1;" : "=f"(s) : "f"(rbf(rbf(v) + 1e-5f)));
    return pack2(s, m);
}
__device__ __forceinline__ float frsq(float x) { float r; asm("rsqrt.approx.ftz.f32 %0, %1;" : "=f"(r) : "f"(x)); return r; }
__device__ __forceinline__ float frcp(float x) { float r; asm("rcp.approx.ftz.f32 %0, %1;" : "=f"(r) : "f"(x)); return r; }
__device__ __forceinline__ bool elect_one() {
    uint32_t p;
    asm volatile("{\n.reg .pred p;\nelect.sync _|p, 0xffffffff;\nselp.u32 %0, 1, 0, p;\n}" : "=r"(p));
    return p != 0;
}
__device__ __forceinline__ void cluster_arrive_relaxed() { asm volatile("barrier.cluster.arrive.relaxed.aligned;" ::: "memory"); }
__device__ __forceinline__ void cluster_wait() { asm volatile("barrier.cluster.wait.aligned;" ::: "memory"); }
__device__ __forceinline__ unsigned long long ld_ll(const unsigned long long* p) {
    unsigned long long v;
    asm volatile("ld.relaxed.gpu.global.b64 %0, [%1];" : "=l"(v) : "l"(p) : "memory");
    return v;
}
__device__ __forceinline__ void st_ll(unsigned long long* p, uint32_t payload, uint32_t tag) {
    const unsigned long long v = (unsigned long long)payload | ((unsigned long long)tag << 32);
    asm volatile("st.relaxed.gpu.global.b64 [%0], %1;" ::"l"(p), "l"(v) : "memory");
}
__device__ __forceinline__ uint4 ld_ll4(const uint4* p) {
    uint4 v;
    asm volatile("{\n.reg .b128 t;\n.reg .b64 a, b;\nld.relaxed.gpu.global.b128 t, [%4];\nmov.b128 {a, b}, t;\nmov.b64 {%0, %1}, a;\nmov.b64 {%2, %3}, b;\n}"
                 : "=r"(v.x), "=r"(v.y), "=r"(v.z), "=r"(v.w) : "l"(p) : "memory");
    return v;
}
__device__ __forceinline__ void st_ll4(uint4* p, uint32_t x, uint32_t y, uint32_t z, uint32_t w) {
    asm volatile("{\n.reg .b128 t;\n.reg .b64 a, b;\nmov.b64 a, {%1, %2};\nmov.b64 b, {%3, %4};\nmov.b128 t, {a, b};\nst.relaxed.gpu.global.b128 [%0], t;\n}"
                 ::"l"(p), "r"(x), "r"(y), "r"(z), "r"(w) : "memory");
}

__device__ __forceinline__ void bulk_s2g(void* dst, uint32_t src, uint32_t bytes) {
    asm volatile("cp.async.bulk.global.shared::cta.bulk_group [%0], [%1], %2;" ::"l"(dst), "r"(src), "r"(bytes) : "memory");
}
__device__ __forceinline__ void bulk_commit() { asm volatile("cp.async.bulk.commit_group;" ::: "memory"); }
__device__ __forceinline__ void bulk_wait() { asm volatile("cp.async.bulk.wait_group 0;" ::: "memory"); }
__device__ __forceinline__ void fence_async_global() { asm volatile("fence.proxy.async.global;" ::: "memory"); }
__device__ __forceinline__ void fence_release() { asm volatile("fence.release.gpu;" ::: "memory"); }
__device__ __forceinline__ void fence_acquire() { asm volatile("fence.acquire.gpu;" ::: "memory"); }
template<int TA, int TB>
__device__ __forceinline__ void wgmma_n192(float (&d)[96], uint64_t da, uint64_t db, int scale_d) {
  asm volatile("{\n.reg .pred p;\nsetp.ne.b32 p, %98, 0;\n"
    "wgmma.mma_async.sync.aligned.m64n192k16.f32.bf16.bf16 "
    "{%0, %1, %2, %3, %4, %5, %6, %7, %8, %9, %10, %11, %12, %13, %14, %15, %16, %17, %18, %19, %20, %21, %22, %23, %24, %25, %26, %27, %28, %29, %30, %31, %32, %33, %34, %35, %36, %37, %38, %39, %40, %41, %42, %43, %44, %45, %46, %47, %48, %49, %50, %51, %52, %53, %54, %55, %56, %57, %58, %59, %60, %61, %62, %63, %64, %65, %66, %67, %68, %69, %70, %71, %72, %73, %74, %75, %76, %77, %78, %79, %80, %81, %82, %83, %84, %85, %86, %87, %88, %89, %90, %91, %92, %93, %94, %95}, %96, %97, p, 1, 1, %99, %100;\n}\n"
    : "+f"(d[0]), "+f"(d[1]), "+f"(d[2]), "+f"(d[3]), "+f"(d[4]), "+f"(d[5]), "+f"(d[6]), "+f"(d[7]), "+f"(d[8]), "+f"(d[9]), "+f"(d[10]), "+f"(d[11]), "+f"(d[12]), "+f"(d[13]), "+f"(d[14]), "+f"(d[15]), "+f"(d[16]), "+f"(d[17]), "+f"(d[18]), "+f"(d[19]), "+f"(d[20]), "+f"(d[21]), "+f"(d[22]), "+f"(d[23]), "+f"(d[24]), "+f"(d[25]), "+f"(d[26]), "+f"(d[27]), "+f"(d[28]), "+f"(d[29]), "+f"(d[30]), "+f"(d[31]), "+f"(d[32]), "+f"(d[33]), "+f"(d[34]), "+f"(d[35]), "+f"(d[36]), "+f"(d[37]), "+f"(d[38]), "+f"(d[39]), "+f"(d[40]), "+f"(d[41]), "+f"(d[42]), "+f"(d[43]), "+f"(d[44]), "+f"(d[45]), "+f"(d[46]), "+f"(d[47]), "+f"(d[48]), "+f"(d[49]), "+f"(d[50]), "+f"(d[51]), "+f"(d[52]), "+f"(d[53]), "+f"(d[54]), "+f"(d[55]), "+f"(d[56]), "+f"(d[57]), "+f"(d[58]), "+f"(d[59]), "+f"(d[60]), "+f"(d[61]), "+f"(d[62]), "+f"(d[63]), "+f"(d[64]), "+f"(d[65]), "+f"(d[66]), "+f"(d[67]), "+f"(d[68]), "+f"(d[69]), "+f"(d[70]), "+f"(d[71]), "+f"(d[72]), "+f"(d[73]), "+f"(d[74]), "+f"(d[75]), "+f"(d[76]), "+f"(d[77]), "+f"(d[78]), "+f"(d[79]), "+f"(d[80]), "+f"(d[81]), "+f"(d[82]), "+f"(d[83]), "+f"(d[84]), "+f"(d[85]), "+f"(d[86]), "+f"(d[87]), "+f"(d[88]), "+f"(d[89]), "+f"(d[90]), "+f"(d[91]), "+f"(d[92]), "+f"(d[93]), "+f"(d[94]), "+f"(d[95])
    : "l"(da), "l"(db), "r"(scale_d), "n"(TA), "n"(TB));
}

template<int TA, int TB>
__device__ __forceinline__ void wgmma_n48(float (&d)[24], uint64_t da, uint64_t db, int scale_d) {
  asm volatile("{\n.reg .pred p;\nsetp.ne.b32 p, %26, 0;\n"
    "wgmma.mma_async.sync.aligned.m64n48k16.f32.bf16.bf16 "
    "{%0, %1, %2, %3, %4, %5, %6, %7, %8, %9, %10, %11, %12, %13, %14, %15, %16, %17, %18, %19, %20, %21, %22, %23}, %24, %25, p, 1, 1, %27, %28;\n}\n"
    : "+f"(d[0]), "+f"(d[1]), "+f"(d[2]), "+f"(d[3]), "+f"(d[4]), "+f"(d[5]), "+f"(d[6]), "+f"(d[7]), "+f"(d[8]), "+f"(d[9]), "+f"(d[10]), "+f"(d[11]), "+f"(d[12]), "+f"(d[13]), "+f"(d[14]), "+f"(d[15]), "+f"(d[16]), "+f"(d[17]), "+f"(d[18]), "+f"(d[19]), "+f"(d[20]), "+f"(d[21]), "+f"(d[22]), "+f"(d[23])
    : "l"(da), "l"(db), "r"(scale_d), "n"(TA), "n"(TB));
}

__device__ __forceinline__ void wgmma_rs80(float (&d)[40], const uint4& a, uint64_t db, int scale_d) {
  asm volatile("{\n.reg .pred p;\nsetp.ne.b32 p, %45, 0;\n"
    "wgmma.mma_async.sync.aligned.m64n80k16.f32.bf16.bf16 {%0,%1,%2,%3,%4,%5,%6,%7,%8,%9,%10,%11,%12,%13,%14,%15,%16,%17,%18,%19,%20,%21,%22,%23,%24,%25,%26,%27,%28,%29,%30,%31,%32,%33,%34,%35,%36,%37,%38,%39}, {%40,%41,%42,%43}, %44, p, 1, 1, 1;\n}\n"
    : "+f"(d[0]), "+f"(d[1]), "+f"(d[2]), "+f"(d[3]), "+f"(d[4]), "+f"(d[5]), "+f"(d[6]), "+f"(d[7]), "+f"(d[8]), "+f"(d[9]), "+f"(d[10]), "+f"(d[11]), "+f"(d[12]), "+f"(d[13]), "+f"(d[14]), "+f"(d[15]), "+f"(d[16]), "+f"(d[17]), "+f"(d[18]), "+f"(d[19]), "+f"(d[20]), "+f"(d[21]), "+f"(d[22]), "+f"(d[23]), "+f"(d[24]), "+f"(d[25]), "+f"(d[26]), "+f"(d[27]), "+f"(d[28]), "+f"(d[29]), "+f"(d[30]), "+f"(d[31]), "+f"(d[32]), "+f"(d[33]), "+f"(d[34]), "+f"(d[35]), "+f"(d[36]), "+f"(d[37]), "+f"(d[38]), "+f"(d[39])
    : "r"(a.x), "r"(a.y), "r"(a.z), "r"(a.w), "l"(db), "r"(scale_d));
}

__device__ const __align__(1024) uint32_t c_fft[11264] = {
0x2ddc2dba,0x2fe62eb5,0x2ed02eb5,0xafffaf6e,0x2e1f2dfe,0x2e3f2fbc,0x2f022ee9,0xad27af30,0x2e5e2e3f,0x1fd92b5e,0x2f302f1a,0x244ea875,0x2e992e7c,0xad96a993,0x2f5a2f46,0x2e992c32,
0xad00ad72,0xa17eac32,0xa17ea515,0xabb79cb6,0xac07ac87,0x2dfe29f1,0x1fd99648,0xafedae99,0xa9f1ab05,0x2fd42fbc,0x26a1244e,0xad96af91,0xa765a8d5,0x2aaa2e3f,0x29932875,0x2515a8d5,
0xae99adfe,0xb000aee9,0xaf6eafbc,0x2c872f30,0xaf80af1a,0xac32af02,0xae7caf02,0xaaaa217e,0xaff4afc9,0x2b5e9cb6,0xad27addc,0xaff4ae7c,0xafedb000,0x2ffc2eb5,0xab05ac5d,0xacd8af5a,
0x2c072d27,0x9fd92bb7,0xadfead00,0x2fed2e1f,0x25db2993,0xaf6eacb0,0xaf6eaed0,0x2c5d2f46,0xa5151648,0xaddcafdd,0xafffafd4,0xac321648,0xabb7a934,0x28d5a814,0xafa0afed,0xaff4af30,
0x2f302e3f,0x2fed2f1a,0x28142b5e,0x2934a875,0x30002fc9,0x26a12ddc,0xa5db1cb6,0x30002e7c,0x2f462fd4,0xaed0aa4e,0xacb0aa4e,0x29932e99,0x2d272e5e,0xae3faffc,0xaf02adfe,0xae1fa814,
0xa9f1acd8,0x26a1ab05,0x2fd42ffc,0xad96afed,0x2515a30e,0x2fff2e1f,0x2ddc2f1a,0x2c32a30e,0x2d272aaa,0x28752e7c,0x28752c32,0x2fa02f80,0x2f912e99,0xaee9a9f1,0xa8141648,0x9fd92c87,
0xafa0ae7c,0xafafaf46,0x2d002993,0xafa0ac32,0xaf91b000,0x244eac5d,0x2fbc2eb5,0xab05af5a,0xac87ae5e,0x30002dfe,0x2f6e2ffc,0x2e992814,0x1cb6a875,0x25152e1f,0x2c322e1f,0x2d722ff4,
0x27652c87,0xa9932a4e,0xaaaaadba,0xa5152c87,0xabb7a44e,0xafa0af30,0x28d59fd9,0xaff4ae5e,0xaf91ae1f,0x2814abb7,0x2ee92d00,0x1fd9ad27,0xaf5aafff,0x2fd42ed0,0x2fd42fe6,0x30002ddc,
0x2f462f6e,0x2c322fdd,0x2e7c2fdd,0xa993b000,0xab5e2934,0xafafacd8,0xad00244e,0x2f1a2dfe,0xaee9afaf,0x2f30a17e,0xadfeaff8,0xafbca30e,0x2c5da765,0xa9f12ddc,0x2d969cb6,0x2c5dacb0,
0x2bb7a993,0x2f1aa515,0x2f1a2765,0xaff4aaaa,0x2e5e2fd4,0xab052dba,0x29342f6e,0x2ee9a6a1,0xadba1fd9,0xa5dbafed,0xafddac07,0xaa4e2dfe,0xacb0aff8,0x2ddc2f02,0x9cb6ae3f,0xa765aff8,
0xaeb5af91,0xaa4eafed,0x9648ae5e,0xac5d2d4d,0x2ddca17e,0x2e7c2e3f,0x2fc92e3f,0x1cb6afa0,0x2bb72fe6,0xaff8a993,0xab5e2aaa,0x2bb72fc9,0xafbcaa4e,0x2f30a5db,0xadfeafdd,0xaee9adba,
0xacd828d5,0xaf91230e,0xaf30af02,0x2c072fa0,0xac5dafff,0x2dbaac32,0x2dbaa515,0xae99addc,0x2fc929f1,0xa9932eb5,0x2aaa2fdd,0x2fe629f1,0xa30e2dfe,0xa17eafed,0xaff8ac07,0xafaf1fd9,
0x2dfe2faf,0x28142ff8,0xae5e217e,0x2ffc230e,0xaf5aa515,0xac87af46,0xa6a1af80,0xaf5a2765,0x1cb6ae99,0x2e7c2dba,0x2fc92dba,0x2ddcac5d,0x2f1a2ee9,0xafafab05,0xad002934,0xab5e2e5e,
0x2dbaa814,0x2fdd9fd9,0x25db2f91,0x2a4eaee9,0x27652faf,0xaf4628d5,0xaf80ae1f,0xa5152faf,0xafa0addc,0x2e3fac32,0x2e3fa515,0xa17eafff,0x2dfea6a1,0xacd82dba,0x244e2f6e,0x29342fd4,
0xad27afc9,0xa30eafff,0x2faf2d72,0xad27ae7c,0x2ffc2a4e,0x28142fdd,0xae5e25db,0x2dfe2dba,0xac5d2c07,0xaa4eaf91,0x9648af30,0xaeb5acd8,0xa993aff4,0x2c322f1a,0x2e7c2f1a,0x2f462bb7,
0xae7c26a1,0xafff1648,0x2d72aa4e,0xafc926a1,0x230eaee9,0x2ff89fd9,0x217e2f91,0x2fafa814,0x2d4d2fa0,0xafed230e,0xae5eaf02,0xaf9128d5,0xb000aaaa,0x2fdda515,0x2fdd2765,0x2f6ea993,
0x9cb63000,0xacb02fd4,0xa7652fd4,0x2ddcaf5a,0x217eaffc,0x2ff4ac07,0x2875afbc,0xaff82934,0xa44e2ff4,0xadfea8d5,0xa9342fa0,0x2cd82bb7,0x25dbafe6,0x16482f46,0x29f1af80,0x25dbafc9,
0x2ff41cb6,0x2e1f2765,0x2e1f2cb0,0xa875addc,0xafbca5db,0x1fd9af5a,0xad4dad96,0xacd82fdd,0x2f5a2934,0xaeb52ee9,0x2c5d2e5e,0x3000ab05,0xaed0ab5e,0x2f80a30e,0xaaaaaf02,0xacb0ab5e,
0x25dbaffc,0x2d96afbc,0x2f5aac07,0xafdd2934,0xaaaa2fa0,0xafc92875,0xafe62875,0x29932d27,0x2d00aed0,0x28d52d72,0x2ff89cb6,0x2d00afe6,0xae5e2d96,0x2d4dafd4,0xaf91a6a1,0xafed29f1,
0xafbca17e,0xad4da875,0x1fd9aff4,0xacd82ff8,0x2e992aaa,0xaa4e2fe6,0xaa4e2fc9,0x2fd4a993,0xacb0ad96,0x2fffac87,0x2d72aeb5,0xa765ad96,0x28752f30,0xab5eac07,0xaf1a2cd8,0xae3f2f91,
0xa9342ff4,0xae5e2fa0,0xaee9a8d5,0x2b052bb7,0x2d96aed0,0x2eb59cb6,0x2c872d72,0x2d96afe6,0xaf802c5d,0x2765af6e,0xa515af6e,0xaf4625db,0x2ff8a44e,0xaff42d4d,0xa8752ffc,0xa17e2ee9,
0x2f5a244e,0x2c5d2934,0xaeb52dfe,0x3000acd8,0xacb0ad00,0x2d72aff8,0x2fffa8d5,0xa765ad00,0x217e2f80,0xaf022515,0xaf02a765,0xaf1a2f46,0x2b05afdd,0xa8142f5a,0x2c072d96,0x2d4d25db,
0x2b5eafe6,0x2f02af80,0x230e2f46,0x2b5eafc9,0xaf302d96,0xacd8a6a1,0x2c07afd4,0xaf9129f1,0x2fdda44e,0xad962ffc,0xaf5a2d4d,0xa5db2ee9,0xad72abb7,0x2e7ca17e,0x2fc9a17e,0x2fffad00,
0xaed0a5db,0xaaaaa9f1,0x2f809648,0xacb0a5db,0x28752e5e,0xaf1a2f91,0xab5ead4d,0xae3f2fed,0x2b05aff8,0x2c072875,0xa8142ff4,0x2d4d217e,0xaf6e2d72,0x2eb5afc9,0x2eb5ae7c,0x2dbaafff,
0xaf802f5a,0xafc92e99,0xafe62e99,0x2f46ad96,0x28d52b05,0xaf022fed,0x230e2cd8,0x2fa0affc,0x2fbcaf02,0xa9342d27,0x2ffcae1f,0x2c07ae3f,0xa6a1ac32,0x2a4e9cb6,0x9648ad72,0xa6a1a515,
0x28752aaa,0xa8d52cb0,0xa8d52ed0,0x2e3faf80,0x2fedaeb5,0x29349648,0x2f30aa4e,0x2814ac5d,0x1648ad4d,0x2e99acd8,0x2c87afbc,0xa9f11fd9,0xafe62d27,0x2fffafaf,0xaddc230e,0xaed02d27,
0x2fd4af30,0x2f6eae5e,0x2dbaa44e,0xa6a19fd9,0x1cb6ad27,0x2fe6aff4,0x2ed0aff4,0xad722b5e,0xafaf2cb0,0x2e1faf46,0xa8d5a993,0xafaf2ed0,0xac072f6e,0x2934ac87,0xaffc2e99,0xafbc3000,
0xa44eab5e,0x2b05ad00,0x2f91afaf,0xafbc2f1a,0xafd42d72,0x1648a765,0x1648acb0,0xafdd2fff,0xac322f5a,0xaaaa26a1,0xaf802c87,0xae7c2f5a,0x2d009fd9,0xae1f2cd8,0xad272fbc,0xabb72d4d,
0xaffc2f02,0xaee92e1f,0x244ead27,0xad4d2e3f,0xa9f12e7c,0xafdd2f80,0xaeb52aaa,0xa9f12c32,0x2d72a5db,0xafe63000,0xaed03000,0x9cb626a1,0x2fa0afbc,0xaf022f91,0x230e2b05,0x28d5a44e,
0x96482c07,0xac872d4d,0xae992b05,0x29f1a814,0x2ed0abb7,0xa9932b5e,0xaf462ff8,0x2cb0abb7,0x2f1aafff,0xa30e2765,0xa30e2cb0,0x2e1fad72,0x1fd9ac5d,0x244e9648,0x2e5eaa4e,0x2f30aeb5,
0x2ff8aed0,0x2e3faddc,0xaf022fff,0x2ff8afe6,0x2d4daf6e,0x2ee9ae99,0xa44e2c87,0x2ffcb000,0xa6a1a814,0x2f6eaf30,0x2dbaa934,0x2fd4afed,0xaf462d00,0x2fc9afa0,0x2fe6afa0,0x2f80afaf,
0x2515ac5d,0x2d72ad96,0x1cb629f1,0x2c32ac5d,0xad002814,0x2d27ad4d,0x2e1fab05,0x2bb7ac07,0xaffc2f1a,0x2cd8ad00,0x2fedafaf,0x2b05ab5e,0xadba2f80,0x2c87acb0,0x2c87aed0,0x2a4eaaaa,
0x2f802f6e,0x2fc92fdd,0x2fe62fdd,0xaf46b000,0x2fa02f91,0x2bb72e5e,0x2ff42fed,0xa8d5ad4d,0x2fbc2faf,0xa934217e,0x2ffc2ff8,0x2c07230e,0x2fd42fc9,0xaf5aad72,0x30002fff,0x2fd42e7c,
0x2bb72aaa,0x2f1a2cb0,0x2f1a2ed0,0xaff4af80,0x2cd82c5d,0x2f303000,0x2f912f5a,0xac07aeb5,0x2dba2d4d,0x25db2cd8,0x2fdd2fbc,0x2a4e9fd9,0x2e7c2e1f,0xad72a875,0x2fff2ff4,0x2fc92e1f,
0xa6a1a934,0x29f1a44e,0x2d962cd8,0xafd4adfe,0x1cb6a17e,0x2fe62e3f,0x2ed02e3f,0xad72afa0,0x28752515,0x2d272f80,0x2fa02f46,0x2875a765,0x2c072a4e,0xa93425db,0x2ffc2fdd,0x2fbc2dba,
0xae5eaf1a,0xa934ae3f,0x2b052875,0xaee9ab5e,0xac5dad72,0x2dba2765,0x2dba2cb0,0xae99afff,0xa765aa4e,0x2f802fd4,0x2f462e99,0x2515aa4e,0x230e9fd9,0x217e2cd8,0x2ff82fbc,0x2faf2d4d,
0xaffcafaf,0xaee9aff8,0x244ea17e,0xad4da30e,0xaf6eafe6,0x25dbaaaa,0x2c5d2993,0xaf6eafc9,0xad72ae99,0x2fe62dba,0x2ed02dba,0x1cb6ac5d,0xa8d5ac07,0x2bb72f30,0x2ff42f91,0x2fa02cd8,
0xadbaac07,0xafddad4d,0xa5dbab05,0xaa4e2814,0xafc9af02,0xaaaaaf1a,0x2993217e,0xafe6af02,0xafa0afff,0x2e3f2765,0x2e3f2cb0,0xa17ead72,0xad4daeb5,0x2e5e3000,0x2fed2f5a,0x2f912c5d,
0xa17e2765,0xad001cb6,0xabb7addc,0xa17e2cb0,0xad4daa4e,0xaee9afdd,0x244ea5db,0xaffcadba,0xafd4aee9,0x29f1a934,0x2d962b05,0xa6a1ae5e,0xaf46aff4,0x2fc92f1a,0x2fe62f1a,0x2f802bb7,
0x2cb02eb5,0x1cb62dba,0xaddcaf6e,0x27652eb5,0xa30e2814,0xaff8ad4d,0xa17eab05,0xafafac07,0xadfeab5e,0xa44eae3f,0x2cd82875,0xa934af1a,0xb000af80,0x2fdd2cb0,0x2fdd2ed0,0x2f6e2aaa,
0x2d723000,0x25152fd4,0x2c322fd4,0x1cb6af5a,0xae1f9fd9,0xae3faee9,0xaf02a814,0x2d272f91,0xacd8aff4,0x2ffc28d5,0xab05afa0,0xafedabb7,0x2e992515,0xad962aaa,0x2f5a2993,0x2e99a765,
0x2ff42ddc,0x2e1f2ed0,0x2e1f2fe6,0xa875afff,0xa8142c87,0xaffca9f1,0xadfe1648,0x2e5e2e99,0xaf5aaf30,0x2eb5a814,0xac5dafed,0xb000a934,0x2c32a8d5,0xa9932e3f,0x2f462875,0x2e7ca8d5,
0x2e991fd9,0x30002814,0x2f6e2ee9,0xac87af91,0x29932fa0,0xaed02875,0xacb02875,0x2f462d27,0xaff4ac32,0x2b5eaddc,0xad27afff,0xaff4a515,0x244ead96,0x1fd92fd4,0x2f3026a1,0x2e5ea9f1,
0x2814ad27,0x2dfeabb7,0x2ffc2d00,0xae5eae1f,0x2e992f80,0xaa4e2e7c,0xaa4e2c32,0x2fd42aaa,0xae7c1648,0x9cb6afdd,0xaddcafd4,0xafc91648,0xa875af91,0x2b5e2fbc,0x2f1a244e,0x2e3fab05,
0xab05aff4,0x244eafa0,0x2fbc28d5,0xaf91abb7,0x30002c32,0x26a12fff,0xa5db2ddc,0x30002515,0xaaaa2c5d,0xac32af6e,0xae7caf6e,0xaf8025db,0xad27afed,0x2e3f2dfe,0x2f021fd9,0x2e1fac07,
0xaf5aae5e,0xac5daf30,0x2eb59fd9,0xb000a44e,0x2e7ca30e,0x2ddc2e1f,0x1cb62f1a,0x2fc9a30e,0x217e2f46,0xaf02acb0,0xaf02aed0,0xaf1a2993,0xaf30ae99,0x2fbc29f1,0x2ee99648,0x2dfeac87,
0xafa0a515,0xafafa993,0x2d00aaaa,0xafa02765,0x2934ad96,0x2fed26a1,0x28142fd4,0x2f30a9f1,0x2c872fed,0xb0009fd9,0xaf6eadfe,0xae992c07,0xafffabb7,0x2fe6a17e,0x2ed0a17e,0x2ddcad00,
0xac322c87,0xaf462a4e,0x2993adba,0xae7c2c87,0xa875afed,0x2f1aab05,0x2b5e2ffc,0x2e3facd8,0x2f302e1f,0xaee92bb7,0xafbcad00,0xadfe2d27,0xaf6e9cb6,0x2eb5ac32,0x2eb5a515,0x2dbaad72,
0xaaaa2f5a,0xaed02e99,0xacb02e99,0x2f80ad96,0x2b5eaf30,0x2fafa44e,0x2d00ae5e,0xaf1a9fd9,0xac072f02,0xab05ad27,0xad4d2e1f,0x28142e3f,0x2c5daed0,0xa9f12fff,0x2d96addc,0x2c5dafe6,
0x28752f80,0xa8d52fe6,0xa8d52fc9,0x2e3faf46,0xa44eafd4,0x2f91adba,0x2b05af6e,0xafbc26a1,0x96482ffc,0xae99a44e,0xac872ee9,0x29f12d4d,0x2515aff8,0x1cb62f02,0x2d72ae3f,0x2c32aff8,
0x2eb52b05,0x2a4e2cd8,0x16482fed,0x2c5daffc,0xad72ad27,0x2cb0aff4,0x2765aff4,0xafff2b5e,0x2bb72e7c,0xaff82aaa,0xab5e2f80,0x2bb72c32,0xa814af6e,0x2b052c87,0x2d4dae99,0x2c07b000,
0x2feda8d5,0x2f30a30e,0x29342f02,0x2814afa0,0xafd49cb6,0x1648aed0,0x1648afe6,0xafdd2d72,0x2ed029f1,0xaf462eb5,0xa9932fdd,0x2cb029f1,0xad00ad4d,0x2e1f244e,0x2d27aee9,0x2bb7affc,
0x2d4daf02,0x2fbcae1f,0x2cd82d27,0x9fd9ae3f,0xaf5a2cb0,0xac87a993,0xa6a1af46,0xaf5a2ed0,0x2fffa5db,0xacb03000,0xa7653000,0x2d7226a1,0xaf1aa814,0x2fafa934,0x2d00af30,0x2b5eafed,
0x1648afbc,0x2c87affc,0x2e992934,0xa9f1ac07,0xac322faf,0xaf8028d5,0xaaaaae1f,0xae7c2faf,0x2f1aad72,0xa30e2ed0,0xa30e2fe6,0x2e1f1cb6,0xaffc26a1,0x2fedadba,0x2cd8af6e,0x2b05afd4,
0xad27ac32,0xa30ead72,0x2faf9cb6,0xad27a515,0x1fd92f6e,0xafbc2e99,0xacd8ac87,0xad4d3000,0x2c5dafbc,0x2a4e2b05,0x16482f91,0x2eb5a44e,0xaf802d00,0x2ed0afa0,0x2cb0afa0,0x2aaaafaf,
0xafe626a1,0xaddc1648,0x2fffaa4e,0xaed026a1,0x2d002c07,0xad272ffc,0xae1fa934,0xabb72fbc,0x1fd9afa0,0x2e5ea30e,0x244e2f02,0x2f30a8d5,0xadba2f46,0x2c87afe6,0x2c87afc9,0x2a4eaf80,
0xafff2d96,0xae7c2c5d,0xafc92c5d,0x2d72a9f1,0xa17e2dfe,0xaff42fbc,0xa8752ee9,0x2ff8af30,0x2fedad00,0xad4d2f1a,0x2f91ab5e,0x2e5eafaf,0x25dbae7c,0x16482993,0x29f1af46,0x25dbac32,
0xae3f2fff,0xaff82fc9,0xaff82e7c,0x2f02ad72,0x2c0725db,0xadfe2f5a,0x9fd92d96,0x2fedafdd,0x2f6eaf91,0xa6a12c07,0x2fd4acd8,0x2dbaaf30,0xa765ab5e,0x2aaaa30e,0x2993af02,0x2515ab5e,
0xa5db2dfe,0xad962ee9,0xaf5a2fbc,0x2fddaf30,0x2f46ab5e,0xa7652bb7,0x25152bb7,0x2f80aff8,0x2d00afc9,0x28d59cb6,0x2ff8addc,0x2d00ae7c,0xacd89648,0x2dfeac5d,0x2934aeb5,0x244eaa4e,
0x2c07217e,0x9fd92875,0xadfe2ff4,0x2fedaff8,0x2fddaf46,0x29f1a515,0x29f12765,0x2eb5af80,0x2515ad96,0x2ddcac87,0x2fffaeb5,0x2c32ad96,0xaf022b05,0x2fa0aee9,0x28d5ae5e,0x230ea934,
0x2f91ad00,0x2cd8ab5e,0xac072f1a,0x2f30afaf,0x2d96afc9,0x2eb5addc,0x2c879cb6,0x2d96ae7c,0xa993a6a1,0x2fc9af5a,0x2fe6af5a,0x2aaaac87,0xaff82e5e,0x2ff4affc,0x2875adfe,0x217ea814,
0x2f6eafed,0x2fd4af91,0xa6a12d4d,0x2dbaae5e,0x2515ad00,0x2fffaff8,0x2ddca8d5,0x2c32ad00,0xae1f2993,0x2fafafe6,0x2fafafc9,0x28d5aaaa,0xaf912fdd,0x2ee9af5a,0x2814ad96,0x1fd9a5db,
0x2b5eae7c,0x2f02af46,0x230e2993,0x2b5eac32,0xab059648,0x2e5eaeb5,0x2ee9ac5d,0x2934aa4e,0xafdd2e5e,0x2d96adfe,0x2f5aaffc,0x25dba814,0xaddc2faf,0x2cb0ad27,0x2765ad27,0x1cb6a30e,
0xa765a5db,0x2993a9f1,0x2aaa9648,0x2515a5db,0xaf022cd8,0x28d5a934,0x2fa0adfe,0x230ea44e,0xaf912ff8,0x2814a875,0x2ee9aff4,0x1fd9a17e,0xaa4e2ddc,0x26a1a765,0x26a1acb0,0x16489cb6,
0x2d722d96,0x25152c5d,0x2c322c5d,0x1cb6a9f1,0x2d272d4d,0xad00a814,0x2bb72c07,0x2e1f2b05,0x2cd82d00,0xaffcaf1a,0x2b052b5e,0x2fed2faf,0x2c872cb0,0xadbaaf80,0x2a4e2aaa,0x2c872ed0,
0x2e3f2ddc,0x2ff82ed0,0x2ff82fe6,0xaf02afff,0x2ee92e99,0x2d4d2f6e,0x2ffc3000,0xa44eac87,0x2f6e2f30,0xa6a12814,0x2fd42fed,0x2dba2934,0x2fc92fa0,0xaf46ad00,0x2f802faf,0x2fe62fa0,
0xac87ad4d,0x9648ac07,0x29f12814,0xae99ab05,0xa993ab5e,0x2ed02bb7,0x2cb02bb7,0xaf46aff8,0xa30ea765,0x2f1a2fff,0x2e1f2d72,0xa30eacb0,0x244e1648,0x1fd92c5d,0x2f302eb5,0x2e5e2a4e,
0xaee9ae1f,0xaffcaf02,0xad4dae3f,0x244e2d27,0xafddaf80,0xa9f1ae7c,0xa9f1ac32,0xaeb5aaaa,0xafe6b000,0x2d7225db,0x9cb6a6a1,0xaed0b000,0xaf02af91,0x2fa02fbc,0x28d5244e,0x230eab05,
0x2b052d00,0xa44e2b5e,0xafbcaf1a,0x2f912faf,0x16482765,0xafd4ad72,0xafddafff,0x16482cb0,0xaaaaa6a1,0xac32af5a,0xae7caf5a,0xaf80ac87,0xae1facd8,0x2d001fd9,0xabb7ad4d,0xad27afbc,
0x2f6e2e5e,0x2fd42f30,0xa6a11fd9,0x2dba244e,0x2fe62ff4,0x1cb62d27,0xad72ab5e,0x2ed02ff4,0x2e1f2f46,0xafafacb0,0xafafaed0,0xa8d52993,0x29342c87,0xac07af6e,0xafbcb000,0xaffcae99,
0xa8d5acb0,0x2875aaaa,0x2e3f2f80,0xa8d5aed0,0x29341648,0x2fed2eb5,0x28142c5d,0x2f302a4e,0x2e992cd8,0x16482d4d,0xa9f19fd9,0x2c872fbc,0x2fff2faf,0xafe6ad27,0xaed0ad27,0xaddca30e,
0xafc9ae99,0xaf80af5a,0x2f462d96,0xafe6ae99,0xaf02afed,0x28d5ab05,0x2fa02ffc,0x230eacd8,0xa934ad27,0x2fbc2f02,0x2c072e3f,0x2ffc2e1f,0x2a4e1cb6,0xa6a12c32,0xa6a12515,0x96482d72,
0xaaaa29f1,0xaed025db,0xacb025db,0x2f801648,0xaf1aaf91,0x2875ae5e,0xae3fafed,0xab5e2d4d,0x2c07a875,0x2b052ff8,0x2d4da17e,0xa814aff4,0x2eb52fc9,0xaf6ead72,0x2dba2fff,0x2eb52e7c,
0x2f022f80,0x2b5e2fe6,0x2b5e2fc9,0x230eaf46,0xacd826a1,0xaf30ad96,0xaf91a9f1,0x2c072fd4,0xad96affc,0x2fdd244e,0xa5dbaee9,0xaf5aad4d,0x2e7c217e,0xad722bb7,0x2fff2d00,0x2fc9217e,
0x2c5da934,0x2f5aa44e,0x30002cd8,0xaeb5adfe,0x2d722ff8,0xacb02d00,0xa7652d00,0x2fff28d5,0xaf02a515,0x217eaf80,0xaf1aaf46,0xaf022765,0xa814af5a,0x2b052fdd,0x2d4da5db,0x2c07ad96,
0xae5eafa0,0xa934aff4,0x2b05abb7,0xaee928d5,0x2eb51cb6,0x2d962ed0,0x2d962fe6,0x2c87ad72,0x27652f6e,0xaf80ac5d,0xaf46a5db,0xa5152f6e,0xaff4ad4d,0x2ff8244e,0xa17eaee9,0xa875affc,
0xad4d2875,0xafbc217e,0xacd8aff8,0x1fd92ff4,0xaa4eafe6,0x2e99aaaa,0x2fd42993,0xaa4eafc9,0x2fff2c87,0xacb02d96,0xa7652d96,0x2d722eb5,0xab5e2c07,0x2875af30,0xae3faf91,0xaf1aacd8,
0x2d962fbc,0x25db2ffc,0xafdda934,0x2f5a2c07,0xafc9a875,0xaaaaafa0,0x2993ad27,0xafe6a875,0x28d5ad72,0x2d002ed0,0x2d002fe6,0x2ff81cb6,0x2d4d2fd4,0xae5ead96,0xafeda9f1,0xaf9126a1,
0x2e1fa765,0x2ff49cb6,0xa8752ddc,0x2e1facb0,0x1fd92f5a,0xafbc25db,0xacd8afdd,0xad4d2d96,0xaeb5aee9,0x2f5aa934,0x30002b05,0x2c5dae5e,0x2f80230e,0xaed02b5e,0xacb02b5e,0xaaaa2f02,
0xacb0afd4,0x9cb6b000,0x2ddc2f5a,0xa765afd4,0x2ff42c07,0x217e2ffc,0xaff8a934,0x28752fbc,0xadfe28d5,0xa44eaff4,0x2cd8abb7,0xa934afa0,0x1648af46,0x25db2fe6,0x25db2fc9,0x29f12f80,
0xafff9648,0xae7ca6a1,0xafc9a6a1,0x2d722a4e,0x2ff81fd9,0x230e2ee9,0x2faf2814,0x217eaf91,0xafeda30e,0x2d4dafa0,0xaf91a8d5,0xae5e2f02,0x2fdd2515,0xb0002aaa,0x2f6e2993,0x2fdda765,
0xa30e2fff,0xad272fc9,0xad272e7c,0x2fafad72,0x2814afdd,0x2ffcaa4e,0x2dfeadba,0xae5ea5db,0xaa4e2f91,0xac5dac07,0xaeb52cd8,0x96482f30,0x2c32af1a,0xa9932ff4,0x2f46abb7,0x2e7caf1a,
0x2fdd1fd9,0x2dba2814,0x2a4e2ee9,0x25dbaf91,0xaf46a8d5,0x2765afaf,0xa515afaf,0xaf802e1f,0x2e3f2c32,0xafa02ddc,0xa17e2fff,0x2e3f2515,0xacd8adba,0x2dfe26a1,0x2934afd4,0x244eaf6e,
0x2814aff8,0x2dfeafaf,0x2ffca30e,0xae5ea17e,0xac872f46,0xaf5a2515,0xaf5aa765,0xa6a12f80,0x2e7cadba,0x1cb62e99,0x2ddc2c5d,0x2fc9adba,0xafaf2b05,0x2f1aaee9,0xab5eae5e,0xad00a934,
0xaf91a30e,0xacd8a8d5,0x2c07afa0,0xaf302f02,0x2dba2c32,0xac5d2fff,0xae992ddc,0x2dba2515,0xa993aeb5,0x2fc9a9f1,0x2fe6a9f1,0x2aaaafdd,0xa17e2fed,0xa30eadfe,0xafaf9fd9,0xaff82c07,
0xaa4e2fed,0xaeb52f91,0xac5dad4d,0x96482e5e,0x2e7cae3f,0x2ddc217e,0x1cb62fa0,0x2fc9ae3f,0xaff82993,0x2bb7afe6,0x2bb7afc9,0xab5eaaaa,0x2f3025db,0xafbc2a4e,0xaee92dba,0xadfe2fdd,
0x2f1a2515,0x2bb72993,0xaff42aaa,0x2f1aa765,0xab05adba,0x2e5eafd4,0x2ee926a1,0x2934af6e,0xa5db2fed,0xadba9fd9,0xaa4eadfe,0xafdd2c07,0x2ddcaf02,0xacb02ff8,0xa7652ff8,0x9cb62e3f,
0x2c32afdd,0x2f46af6e,0xa9933000,0x2e7cafdd,0xafaf2cd8,0xab5ea934,0x2f1aadfe,0xad00a44e,0x2f30217e,0xaee92faf,0xafbc230e,0xadfe2ff8,0xa9f1addc,0x2c5d2765,0x2c5d2cb0,0x2d961cb6,
0xa993aa4e,0x2765ac87,0xa515ac87,0xaaaa2dba,0xafa02f30,0xabb7244e,0xaff42e5e,0x28d51fd9,0x28142bb7,0xaf912e1f,0x1fd92d27,0x2ee9ad00,0x2fd4aed0,0xaf5a2fff,0x3000addc,0x2fd4afe6,
0xafaf2f46,0xafa02e7c,0xafa02c32,0x2d00a993,0x244e2c5d,0xaf913000,0xab052f5a,0x2fbcaeb5,0x3000adfe,0xac872e5e,0x2e99a814,0x2f6eaffc,0x2515ae1f,0x1cb62875,0x2d72aff4,0x2c32ae1f,
0x26a12b05,0xa9f12cd8,0xad962fed,0x2fd4affc,0x2fffae1f,0x2515230e,0x2c32230e,0x2ddcaf1a,0x2875ae7c,0x2d27aaaa,0x2fa0af80,0x2875ac32,0xaee929f1,0x2f91ae99,0x9fd9ac87,0xa8149648,
0x2fedaf1a,0x2f30ae3f,0x29342875,0x2814ab5e,0x26a1addc,0x3000afc9,0x3000ae7c,0xa5db9cb6,0xaed02a4e,0x2f46afd4,0x2993ae99,0xacb02a4e,0xae3f2ffc,0x2d27ae5e,0xae1f2814,0xaf022dfe,
0x9fd9abb7,0x2c07ad27,0x2fedae1f,0xadfe2d00,0xaf6e2cb0,0x25dba993,0x2c5daf46,0xaf6e2ed0,0xaddc2fdd,0xa5159648,0xac329648,0xafff2fd4,0x28d52814,0xabb72934,0xaff42f30,0xafa02fed,
0xb0002ee9,0xae992dfe,0x2c87af30,0xaf6e2fbc,0xac322f02,0xaf802f1a,0xaaaaa17e,0xae7c2f02,0x2b5e1cb6,0xaff42fc9,0xaff42e7c,0xad272ddc,0x2ffcaeb5,0xafed3000,0xacd82f5a,0xab052c5d,
0xa17e2c32,0xad002d72,0xabb71cb6,0xa17e2515,0x2dfea9f1,0xac072c87,0xafed2e99,0x1fd91648,0x2fd4afbc,0xa9f12b05,0xad962f91,0x26a1a44e,0x2aaaae3f,0xa76528d5,0x251528d5,0x2993a875,
0x2fe6aeb5,0x2ddcadba,0xafff2f6e,0x2ed0aeb5,0x2e3fafbc,0x2e1fadfe,0xad272f30,0x2f02aee9,0x1fd9ab5e,0x2e5eae3f,0x244e2875,0x2f30af1a,0xad962993,0x2e99ae7c,0x2e99ac32,0x2f5aaf46,
0x299329f1,0xa76525db,0x251525db,0x2aaa1648,0x28d52934,0xaf02acd8,0x230e244e,0x2fa02dfe,0x28142875,0xaf91aff8,0x1fd9217e,0x2ee92ff4,0x26a12765,0xaa4eaddc,0x16481cb6,0x26a12cb0,
0x2f022f46,0x2b5e2e7c,0x2b5e2c32,0x230ea993,0x2e5e2eb5,0xab051648,0x29342a4e,0x2ee92c5d,0x2d962dfe,0xafddae5e,0x25db2814,0x2f5a2ffc,0x2cb02d27,0xaddcafaf,0x1cb6230e,0x27652d27,
0x2fd42f91,0x2f6e2fed,0x2dba2e5e,0xa6a1ad4d,0x2fff2ff8,0x25152d00,0x2c322d00,0x2ddc28d5,0x2faf2fe6,0xae1fa993,0x28d52aaa,0x2faf2fc9,0x2ee92f5a,0xaf91afdd,0x1fd925db,0x28142d96,
0x2cd82b5e,0x2f912d00,0x2f302faf,0xac07af1a,0x2eb52ddc,0x2d962fc9,0x2d962e7c,0x2c871cb6,0x2fc92f5a,0xa99326a1,0x2aaa2c87,0x2fe62f5a,0x2ff42ffc,0xaff8ae5e,0x217e2814,0x28752dfe,
0x9fd9a875,0x2c07a17e,0x2fed2ff8,0xadfeaff4,0x29f12515,0x2fdd2f46,0x2eb52f80,0x29f1a765,0x2ddc2c87,0x25152d96,0x2c322d96,0x2fff2eb5,0x2fa02ee9,0xaf02ab05,0x230e2934,0x28d52e5e,
0xad96aee9,0xa5dbadfe,0x2fdd2f30,0xaf5aafbc,0xa765abb7,0x2f462b5e,0x2f802ff8,0x2515abb7,0x28d51cb6,0x2d002fc9,0x2d002e7c,0x2ff82ddc,0x2dfe2c5d,0xacd81648,0x244e2a4e,0x29342eb5,
0xaff8afc9,0xae3fafff,0x2f022d72,0xaff8ae7c,0xadfeaf5a,0x2c07a5db,0x2fed2fdd,0x9fd9ad96,0xa6a1ac07,0x2f6e2f91,0x2dba2f30,0x2fd42cd8,0x2aaa230e,0xa7652b5e,0x25152b5e,0x29932f02,
0xae7cac5d,0xafffad96,0x2d7229f1,0xafc9ac5d,0xaff4afbc,0xa17eadfe,0x2ff82f30,0xa875aee9,0xad4daf1a,0x2fed2d00,0x2e5e2faf,0x2f912b5e,0x1648a993,0x25db2e7c,0x25db2c32,0x29f12f46,
0xaddc9648,0xafe6a6a1,0xaed0a6a1,0x2fff2a4e,0xad27affc,0x2d00ac07,0xabb7afbc,0xae1f2934,0x2e5e230e,0x1fd92fa0,0x2f3028d5,0x244eaf02,0x2c872fe6,0xadbaaf46,0x2a4e2f80,0x2c872fc9,
0xa30e2d72,0xad272c32,0xad272515,0x2faf1cb6,0xafbcae99,0x1fd9af6e,0xad4db000,0xacd82c87,0x2a4eab05,0x2c5d2fbc,0x2eb5244e,0x1648af91,0x2ed02fa0,0xaf80ad00,0x2aaa2faf,0x2cb02fa0,
0x2c872ffc,0x16482fbc,0xa9f12c07,0x2e99a934,0xaf80a8d5,0xac32afaf,0xae7cafaf,0xaaaa2e1f,0xa30eaed0,0x2f1a2d72,0x2e1f9cb6,0xa30eafe6,0x2fed2dba,0xaffca6a1,0x2b052fd4,0x2cd82f6e,
0x2fbc2e1f,0x2d4d2f02,0x9fd92e3f,0x2cd8ad27,0xac872993,0xaf5aacb0,0xaf5aaed0,0xa6a12f46,0xacb0b000,0x2fff25db,0x2d72a6a1,0xa765b000,0x2faf2934,0xaf1a2814,0x2b5e2fed,0x2d002f30,
0x2f30230e,0x2fed28d5,0x28142fa0,0x2934af02,0x16482ed0,0xafd41cb6,0xafddad72,0x16482fe6,0xaf46aeb5,0x2ed0a9f1,0x2cb0a9f1,0xa993afdd,0x2e1fa44e,0xad002d4d,0x2bb72ffc,0x2d272ee9,
0x2a4eacd8,0x2eb5ab05,0x2c5d2ffc,0x1648afed,0x2cb02ff4,0xad722d27,0xafffab5e,0x27652ff4,0xaff8aaaa,0x2bb7ae7c,0x2bb7ac32,0xab5eaf80,0x2b05ac87,0xa8142f6e,0x2c073000,0x2d4d2e99,
0xa8d5afe6,0x2875af80,0x2e3f2f46,0xa8d5afc9,0x2f912dba,0xa44e2fd4,0xafbca6a1,0x2b052f6e,0xae99244e,0x9648affc,0x29f1ad4d,0xac87aee9,0x1cb6af02,0x25152ff8,0x2c322ff8,0x2d722e3f,
0xaed0ae99,0xaaaaaf5a,0x2f802d96,0xacb0ae99,0x2faf244e,0x2b5e2f30,0xaf1a1fd9,0x2d002e5e,0xab052d27,0xac07af02,0x2814ae3f,0xad4dae1f,0xa9f1afff,0x2c5d2ed0,0x2c5d2fe6,0x2d962ddc,
0xaf46aa4e,0xac32ac87,0xae7cac87,0x29932dba,0x2f1a2b05,0xa8752fed,0x2e3f2cd8,0x2b5eaffc,0xaee9abb7,0x2f30ae1f,0xadfead27,0xafbc2d00,0x2eb52c32,0xaf6e1cb6,0x2dba2d72,0x2eb52515,
0xafaf2993,0xafa02515,0xafa0a765,0x2d002aaa,0x2feda6a1,0x29342d96,0x2f3029f1,0x2814afd4,0xb0001fd9,0x2c87afed,0xae99ac07,0xaf6e2dfe,0x2fe6217e,0xafff2bb7,0x2ddc2d00,0x2ed0217e,
0xac5d2f30,0xaf5a2e5e,0xb000244e,0x2eb51fd9,0x2ddcae1f,0x2e7c230e,0x2fc9230e,0x1cb6af1a,0xaf022cb0,0x217eaf46,0xaf1aa993,0xaf022ed0,0x2fbca9f1,0xaf302e99,0x2dfe2c87,0x2ee91648,
0x244e2fa0,0xab052ff4,0xaf912bb7,0x2fbca8d5,0x26a1afff,0x3000ac32,0x3000a515,0xa5dbaddc,0xac322f6e,0xaaaaac5d,0xaf80a5db,0xae7c2f6e,0x2e3fadfe,0xad272fed,0x2e1f2c07,0x2f029fd9,
0x2dfe2bb7,0x28142d27,0xae5e2e1f,0x2ffcad00,0xaa4eae7c,0x2e99af80,0x2fd4aaaa,0xaa4eac32,0x9cb62fdd,0xae7c9648,0xafc99648,0xaddc2fd4,0x2b5eafbc,0xa8752f91,0x2e3f2b05,0x2f1aa44e,
0x3000a814,0x2e999fd9,0xac872f91,0x2f6eaee9,0xaed0a875,0x2993afa0,0x2f46ad27,0xacb0a875,0x2b5e2ddc,0xaff42c32,0xaff42515,0xad272fff,0x1fd9afd4,0x244e2d96,0x2e5e29f1,0x2f30a6a1,
0x2e1faed0,0x2ff4addc,0xa8752fff,0x2e1fafe6,0xaffc29f1,0xa814ac87,0x2e5eae99,0xadfe9648,0x2eb52814,0xaf5a2f30,0xb0002934,0xac5d2fed,0xa993ae3f,0x2c3228d5,0x2e7c28d5,0x2f46a875,
0x2515afd4,0x2d72b000,0x1cb62f5a,0x2c32afd4,0xae3f2ee9,0xae1f1fd9,0x2d27af91,0xaf022814,0x2ffca8d5,0xacd82ff4,0xafed2bb7,0xab052fa0,0xad96aaaa,0x2e99a515,0x2e992765,0x2f5aa993,
0x1cb6adba,0x2cb0aeb5,0x2765aeb5,0xaddc2f6e,0xaff82d4d,0xa30ea814,0xafaf2c07,0xa17e2b05,0xa44e2e3f,0xadfe2b5e,0xa9342f1a,0x2cd8a875,0x2fddacb0,0xb0002f80,0x2f6eaaaa,0x2fddaed0,
0xad009cb6,0xa17ea765,0xa17eacb0,0xabb72ddc,0xaee92fdd,0xad4d2a4e,0xaffc2dba,0x244e25db,0x29f12934,0xafd42ee9,0xa6a12e5e,0x2d96ab05,0x2fc9af1a,0xaf462ff4,0x2f80abb7,0x2fe6af1a,
0xafdd2d4d,0xadba2c07,0xaa4ea814,0xa5db2b05,0xaaaa2f1a,0xafc92f02,0xafe62f02,0x2993a17e,0x2e3fa765,0xafa02fff,0xa17e2d72,0x2e3facb0,0x2e5eb000,0xad4d2eb5,0x2f91ac5d,0x2fedaf5a,
0xaee92ff8,0xaffc2faf,0xad4d230e,0x244e217e,0x25db2aaa,0xaf6e2fe6,0xaf6e2fc9,0x2c5da993,0x2fe6adba,0xad722e99,0x1cb62c5d,0x2ed0adba,0x2bb7af30,0xa8d52c07,0x2fa0acd8,0x2ff4af91,
0xa9342e3f,0xae5e2f1a,0xaee92b5e,0x2b05a875,0x2dbaa765,0xac5d2d72,0xae992fff,0x2dbaacb0,0x2f80afd4,0xa7652a4e,0x25152a4e,0x2f46ae99,0x217eacd8,0x230e1fd9,0x2fafad4d,0x2ff8afbc,
0x29f1244e,0xa6a12934,0xafd42dfe,0x2d96acd8,0x2fe6ae3f,0x1cb6217e,0xad722fa0,0x2ed0ae3f,0x2d27af80,0x2875a515,0x28752765,0x2fa0af46,0xa934a5db,0x2c07aa4e,0x2fbcadba,0x2ffcafdd,
0x2f1aacb0,0x2bb7aaaa,0xaff42f80,0x2f1aaed0,0x2f30b000,0x2cd8ac5d,0xac072eb5,0x2f91af5a,0x25dbacd8,0x2dbaad4d,0x2a4e1fd9,0x2fddafbc,0xad722875,0x2e7cae1f,0x2fc9ae1f,0x2fffaff4,
0x2fc9afdd,0x2f80af6e,0xaf463000,0x2fe6afdd,0x2bb7ae5e,0x2fa0af91,0xa8d52d4d,0x2ff4afed,0xa934a17e,0x2fbcafaf,0x2c07a30e,0x2ffcaff8,0xaf5a2d72,0x2fd4afc9,0x2fd4ae7c,0x3000afff,
0x9d4d9e16,0xada6ae7d,0x9b769c84,0xabf0accf,0x985299e4,0xa897aa43,0x90b6957f,0xa102a5d8,0x13db0a48,0x242c1aad,0x191b1712,0x296d2783,0x1c201aad,0x2c632b1a,0x1db21ce9,0x2e112d3a,
0xa3f4a491,0xae51af42,0xa199a2c6,0xac70ad60,0x9e7ba06b,0xa922ab00,0x97129c20,0xa199a688,0x19e410b6,0x24aa1b76,0x1fa81d4d,0x2a112833,0x222f2102,0x2ce82bf0,0x2445235d,0x2ec92dd8,
0xa6a1a79c,0xaefcb004,0xa4aaa5a5,0xace8adf2,0xa166a35d,0xa9acabbe,0x99e49edf,0xa22fa738,0x1ce913db,0x25281c20,0x2262206b,0x2ab528a4,0x2528242c,0x2d6d2c63,0x271f2623,0x2f822e77,
0xa8a4a954,0xafa8b067,0xa688a7e8,0xad60ae84,0xa38fa528,0xaa37ac3d,0x9c20a0d0,0xa2c6a7e8,0x1edf157f,0x25a51c84,0x2478222f,0x2b592915,0x273825d8,0x2df22ccf,0x28fc284c,0x301d2f16,
0xa9f8aadb,0xb02ab0ca,0xa833a915,0xadd8af16,0xa4dca6a1,0xaac1ac9c,0x9d4da22f,0xa35da84c,0x206b1712,0x26231ce9,0x25bf23f4,0x2bfd2987,0x28a42783,0x2e772d3a,0x2a692987,0x307a2fb5,
0xab4cac31,0xb081b12e,0xa922aa37,0xae51afa8,0xa5f1a80d,0xab4cacfb,0x9e7ba38f,0xa3f4a8a4,0x21661852,0x26a11d4d,0x270524dc,0x2c5029f8,0x29ac2897,0x2efc2da6,0x2bd72ac1,0x30d7302a,
0xac50acf5,0xb0d7b192,0xaa11ab59,0xaec9b01d,0xa705a8ca,0xabd7ad5a,0x9fa8a478,0xa445a8fc,0x2262191b,0x271f1db2,0x282625bf,0x2ca22a69,0x2ab5296d,0x2f822e11,0x2ca22bfd,0x3135307a,
0xacfbadb9,0xb12eb1f7,0xab00ac3d,0xaf42b067,0xa80da987,0xac31adb9,0xa06ba528,0xa491a954,0x235d19e4,0x279c1e16,0x28ca26a1,0x2cf52adb,0x2bbe2a43,0x30042e7d,0x2d5a2c9c,0x319230ca,
0xb185b25c,0xb426b4cc,0xafbbb0b1,0xb1c6b306,0xac76ae18,0xaea3b08a,0xa4dca9ac,0xa738ac37,0x280d1e7b,0x2a0520d0,0x2d472b4c,0x2fdb2d6d,0x30472ee9,0x32663128,0x31f0311b,0x347933a8,
0xb1ddb2c1,0xb453b501,0xb01ab0fb,0xb204b352,0xacbcae77,0xaee9b0ba,0xa528aa05,0xa783ac63,0x284c1edf,0x2a432102,0x2d992bbe,0x30172da6,0x308a2f55,0x32aa315f,0x324f316b,0x34aa33fc,
0xb235b327,0xb481b537,0xb057b145,0xb242b39e,0xad01aed6,0xaf2fb0eb,0xa573aa5d,0xa7cfac90,0x288b1f44,0x2a822134,0x2deb2c18,0x30412ddf,0x30ce2fc2,0x32ef3196,0x32ae31bc,0x34db3428,
0xb28db38e,0xb4afb56d,0xb094b18f,0xb280b3eb,0xad47af36,0xaf75b11b,0xa5bfaab5,0xa80dacbc,0x28ca1fa8,0x2ac12166,0x2e3e2c50,0x306a2e18,0x31113017,0x333531cd,0x330d320e,0x350d3452,
0xb2e5b3f5,0xb4ddb5a3,0xb0d1b1da,0xb2beb41c,0xad8caf95,0xafbbb14b,0xa60aab0d,0xa833ace8,0x29092006,0x2b002199,0x2e902c89,0x30942e51,0x3155304d,0x337a3204,0x336d325f,0x3540347c,
0xb33eb42e,0xb50cb5da,0xb10eb224,0xb2fcb443,0xadd2aff5,0xb001b17c,0xa655ab65,0xa859ad14,0x29482039,0x2b4021cb,0x2ee32cc2,0x30be2e8a,0x31993084,0x33c0323b,0x33cd32b1,0x357234a6,
0xb398b463,0xb53ab612,0xb14bb26f,0xb33bb469,0xae18b02a,0xb024b1ac,0xa6a1abbe,0xa87ead40,0x2987206b,0x2b7f21fd,0x2f362cfb,0x30e72ec3,0x31dd30ba,0x34033273,0x34173303,0x35a534d1,
0xb3f2b497,0xb569b64a,0xb189b2bb,0xb37ab490,0xae5eb05a,0xb047b1dd,0xa6ecac0b,0xa8a4ad6d,0x29c6209d,0x2bbe222f,0x2f882d34,0x31112efc,0x322130f1,0x342632aa,0x34483356,0x35d934fc,
0xb599b682,0xb722b82e,0xb3b9b4b7,0xb4ddb5f9,0xb06ab20e,0xb185b398,0xa8caad99,0xa9f8aefc,0x2bfd2262,0x2cfb23f4,0x313b2f36,0x328d3081,0x344932e2,0x35693453,0x360d3527,0x37bd368b,
0xb5c9b6bb,0xb755b84d,0xb3f8b4df,0xb4feb622,0xb08db23e,0xb1a9b3ca,0xa8f0adc5,0xaa1eaf29,0x2c1e2294,0x2d1b2413,0x31652f6f,0x32b7309d,0x346d331a,0x358e3470,0x36413553,0x37f536ba,
0xb5f9b6f5,0xb789b86d,0xb41cb506,0xb51fb64c,0xb0b1b26f,0xb1cdb3fc,0xa915adf2,0xaa43af55,0x2c3d22c6,0x2d3a242c,0x318f2fa8,0x32e230ba,0x34903352,0x35b3348d,0x3676357e,0x381736e8,
0xb629b72f,0xb7bdb88d,0xb43cb52e,0xb540b676,0xb0d4b2a1,0xb1f0b417,0xa93bae1e,0xaa69af82,0x2c5d22f9,0x2d5a2445,0x31b92fe2,0x330d30d7,0x34b4338b,0x35d934aa,0x36ab35ab,0x38343717,
0xb65ab76a,0xb7f1b8ad,0xb45cb556,0xb561b6a0,0xb0f7b2d2,0xb214b430,0xa961ae4b,0xaa8fafaf,0x2c7d232b,0x2d79245f,0x31e3300e,0x333830f4,0x34d833c3,0x35fe34c7,0x36e035d7,0x38513746,
0xb68bb7a5,0xb813b8ce,0xb47cb57e,0xb582b6ca,0xb11bb303,0xb238b449,0xa987ae77,0xaab5afdb,0x2c9c235d,0x2d992478,0x320e302a,0x33633111,0x34fc33fc,0x362434e4,0x37173604,0x386f3775,
0xb6bdb7e2,0xb82eb8f0,0xb49cb5a7,0xb5a3b6f5,0xb13eb335,0xb25cb463,0xa9acaea3,0xaadbb004,0x2cbc238f,0x2db92491,0x32383047,0x338e312e,0x3520341a,0x364a3501,0x374d3631,0x388d37a5,
0xb6efb80f,0xb849b911,0xb4bdb5d0,0xb5c5b720,0xb162b366,0xb280b47c,0xa9d2aed0,0xab00b01a,0x2cdb23c2,0x2dd824aa,0x32623064,0x33b9314b,0x35453437,0x3670351f,0x3785365e,0x38ab37d6,
0xb865b934,0xb94dba5c,0xb5e7b74c,0xb6fcb85a,0xb2a4b495,0xb3c6b564,0xab26b031,0xac2bb0e4,0x2df824c3,0x2ef6258c,0x33e43168,0x34a13252,0x3697353c,0x37d4362d,0x38ca3803,0x39d038d0,
0xb880b957,0xb96bba84,0xb609b777,0xb720b872,0xb2c8b4af,0xb3ebb57e,0xab4cb047,0xac3db0fb,0x2e1824dc,0x2f1625a5,0x34083185,0x34b7326f,0x36bd355a,0x37fd364c,0x38e9381c,0x39f338eb,
0xb89cb97a,0xb98abaad,0xb62bb7a4,0xb744b88a,0xb2ecb4c9,0xb408b599,0xab72b05d,0xac50b111,0x2e3724f5,0x2f3625bf,0x341e31a2,0x34ce328d,0x36e43577,0x3813366b,0x39093835,0x3a173906,
0xb8b9b99e,0xb9aabad7,0xb64db7d0,0xb768b8a2,0xb310b4e2,0xb41ab5b3,0xab98b074,0xac63b128,0x2e57250f,0x2f5525d8,0x343331c0,0x34e432aa,0x370b3595,0x3828368a,0x3929384e,0x3a3b3922,
0xb8d6b9c3,0xb9cabb02,0xb670b7fd,0xb78cb8ba,0xb335b4fc,0xb42db5ce,0xabbeb08a,0xac76b13e,0x2e772528,0x2f7525f1,0x344931dd,0x34fa32c8,0x373335b3,0x383d36a9,0x39493868,0x3a60393e,
0xb8f3b9e8,0xb9ebbb2d,0xb693b815,0xb7b1b8d2,0xb359b516,0xb43fb5e9,0xabe3b0a1,0xac89b155,0x2e972541,0x2f95260a,0x345f31fa,0x351132e5,0x375b35d2,0x385236c8,0x396a3881,0x3a86395a,
0xb910ba0e,0xba0cbb59,0xb6b6b82c,0xb7d6b8eb,0xb37db530,0xb452b604,0xac05b0b7,0xac9cb16b,0x2eb6255a,0x2fb52623,0x34753217,0x35273303,0x378335f0,0x386836e8,0x398c389b,0x3aac3977,
0xb92eba35,0xba2dbb87,0xb6d9b843,0xb7fbb904,0xb3a2b54a,0xb464b61e,0xac18b0ce,0xacafb182,0x2ed62573,0x2fd5263c,0x348b3235,0x353e3321,0x37ab360e,0x387d3708,0x39ae38b6,0x3ad33994,
0x9ce99db2,0xad3aae11,0x9aad9c20,0xab1aac63,0x9712991b,0xa783a96d,0x8a4893db,0x9aada42c,0x157f10b6,0x25d82102,0x19e41852,0x2a432897,0x1c841b76,0x2ccf2bf0,0x1e161d4d,0x2e7d2da6,
0xa35da445,0xadd8aec9,0xa102a22f,0xabf0ace8,0x9d4d9fa8,0xa833aa11,0x90b699e4,0x9b76a4aa,0x1c201712,0x26882199,0x206b1e7b,0x2b002922,0x22c62199,0x2d602c70,0x249123f4,0x2f422e51,
0xa623a71f,0xae77af82,0xa42ca528,0xac63ad6d,0xa06ba262,0xa8a4aab5,0x93db9ce9,0x9c20a528,0x1edf19e4,0x2738222f,0x235d2166,0x2bbe29ac,0x25a524aa,0x2df22ce8,0x279c26a1,0x30042efc,
0xa84ca8fc,0xaf16b01d,0xa5d8a738,0xaccfadf2,0xa22fa478,0xa915ab59,0x957f9edf,0x9c84a5a5,0x20d01c20,0x27e822c6,0x2528238f,0x2c3d2a37,0x27e82688,0x2e842d60,0x295428a4,0x30672fa8,
0xa987aa69,0xafb5b07a,0xa783a8a4,0xad3aae77,0xa3f4a5bf,0xa987abfd,0x9712a06b,0x9ce9a623,0x222f1d4d,0x284c235d,0x26a124dc,0x2c9c2ac1,0x29152833,0x2f162dd8,0x2adb29f8,0x30ca302a,
0xaac1abd7,0xb02ab0d7,0xa897a9ac,0xada6aefc,0xa4dca705,0xa9f8ac50,0x9852a166,0x9d4da6a1,0x238f1e7b,0x28a423f4,0x280d25f1,0x2cfb2b4c,0x2a372922,0x2fa82e51,0x2c312b4c,0x312e3081,
0xabfdaca2,0xb07ab135,0xa96daab5,0xae11af82,0xa5bfa826,0xaa69aca2,0x991ba262,0x9db2a71f,0x24781fa8,0x28fc2445,0x28ca2705,0x2d5a2bd7,0x2b592a11,0x301d2ec9,0x2cf52c50,0x319230d7,
0xac9cad5a,0xb0cab192,0xaa43abbe,0xae7db004,0xa6a1a8ca,0xaadbacf5,0x99e4a35d,0x9e16a79c,0x2528206b,0x29542491,0x2987280d,0x2db92c31,0x2c3d2b00,0x30672f42,0x2db92cfb,0x31f7312e,
0xb11bb1f0,0xb3a8b479,0xaee9b047,0xb128b266,0xab4cad47,0xad6dafdb,0x9e7ba80d,0xa0d0aa05,0x29ac24dc,0x2c372738,0x2e182c76,0x308a2ea3,0x30b12fbb,0x330631c6,0x325c3185,0x34cc3426,
0xb16bb24f,0xb3fcb4aa,0xaf55b08a,0xb15fb2aa,0xabbead99,0xada6b017,0x9edfa84c,0xa102aa43,0x2a052528,0x2c632783,0x2e772cbc,0x30ba2ee9,0x30fb301a,0x33523204,0x32c131dd,0x35013453,
0xb1bcb2ae,0xb428b4db,0xafc2b0ce,0xb196b2ef,0xac18adeb,0xaddfb041,0x9f44a88b,0xa134aa82,0x2a5d2573,0x2c9027cf,0x2ed62d01,0x30eb2f2f,0x31453057,0x339e3242,0x33273235,0x35373481,
0xb20eb30d,0xb452b50d,0xb017b111,0xb1cdb335,0xac50ae3e,0xae18b06a,0x9fa8a8ca,0xa166aac1,0x2ab525bf,0x2cbc280d,0x2f362d47,0x311b2f75,0x318f3094,0x33eb3280,0x338e328d,0x356d34af,
0xb25fb36d,0xb47cb540,0xb04db155,0xb204b37a,0xac89ae90,0xae51b094,0xa006a909,0xa199ab00,0x2b0d260a,0x2ce82833,0x2f952d8c,0x314b2fbb,0x31da30d1,0x341c32be,0x33f532e5,0x35a334dd,
0xb2b1b3cd,0xb4a6b572,0xb084b199,0xb23bb3c0,0xacc2aee3,0xae8ab0be,0xa039a948,0xa1cbab40,0x2b652655,0x2d142859,0x2ff52dd2,0x317c3001,0x3224310e,0x344332fc,0x342e333e,0x35da350c,
0xb303b417,0xb4d1b5a5,0xb0bab1dd,0xb273b403,0xacfbaf36,0xaec3b0e7,0xa06ba987,0xa1fdab7f,0x2bbe26a1,0x2d40287e,0x302a2e18,0x31ac3024,0x326f314b,0x3469333b,0x34633398,0x3612353a,
0xb356b448,0xb4fcb5d9,0xb0f1b221,0xb2aab426,0xad34af88,0xaefcb111,0xa09da9c6,0xa22fabbe,0x2c0b26ec,0x2d6d28a4,0x305a2e5e,0x31dd3047,0x32bb3189,0x3490337a,0x349733f2,0x364a3569,
0xb527b60d,0xb68bb7bd,0xb2e2b449,0xb453b569,0xaf36b13b,0xb081b28d,0xa262abfd,0xa3f4acfb,0x2d9928ca,0x2efc29f8,0x320e306a,0x33983185,0x34b733b9,0x35f934dd,0x36823599,0x382e3722,
0xb553b641,0xb6bab7f5,0xb31ab46d,0xb470b58e,0xaf6fb165,0xb09db2b7,0xa294ac1e,0xa413ad1b,0x2dc528f0,0x2f292a1e,0x323e308d,0x33ca31a9,0x34df33f8,0x362234fe,0x36bb35c9,0x384d3755,
0xb57eb676,0xb6e8b817,0xb352b490,0xb48db5b3,0xafa8b18f,0xb0bab2e2,0xa2c6ac3d,0xa42cad3a,0x2df22915,0x2f552a43,0x326f30b1,0x33fc31cd,0x3506341c,0x364c351f,0x36f535f9,0x386d3789,
0xb5abb6ab,0xb717b834,0xb38bb4b4,0xb4aab5d9,0xafe2b1b9,0xb0d7b30d,0xa2f9ac5d,0xa445ad5a,0x2e1e293b,0x2f822a69,0x32a130d4,0x341731f0,0x352e343c,0x36763540,0x372f3629,0x388d37bd,
0xb5d7b6e0,0xb746b851,0xb3c3b4d8,0xb4c7b5fe,0xb00eb1e3,0xb0f4b338,0xa32bac7d,0xa45fad79,0x2e4b2961,0x2faf2a8f,0x32d230f7,0x34303214,0x3556345c,0x36a03561,0x376a365a,0x38ad37f1,
0xb604b717,0xb775b86f,0xb3fcb4fc,0xb4e4b624,0xb02ab20e,0xb111b363,0xa35dac9c,0xa478ad99,0x2e772987,0x2fdb2ab5,0x3303311b,0x34493238,0x357e347c,0x36ca3582,0x37a5368b,0x38ce3813,
0xb631b74d,0xb7a5b88d,0xb41ab520,0xb501b64a,0xb047b238,0xb12eb38e,0xa38facbc,0xa491adb9,0x2ea329ac,0x30042adb,0x3335313e,0x3463325c,0x35a7349c,0x36f535a3,0x37e236bd,0x38f0382e,
0xb65eb785,0xb7d6b8ab,0xb437b545,0xb51fb670,0xb064b262,0xb14bb3b9,0xa3c2acdb,0xa4aaadd8,0x2ed029d2,0x301a2b00,0x33663162,0x347c3280,0x35d034bd,0x372035c5,0x380f36ef,0x39113849,
0xb803b8ca,0xb8d0b9d0,0xb53cb697,0xb62db7d4,0xb168b3e4,0xb252b4a1,0xa4c3adf8,0xa58caef6,0x30312b26,0x30e42c2b,0x349532a4,0x356433c6,0x374c35e7,0x385a36fc,0x39343865,0x3a5c394d,
0xb81cb8e9,0xb8ebb9f3,0xb55ab6bd,0xb64cb7fd,0xb185b408,0xb26fb4b7,0xa4dcae18,0xa5a5af16,0x30472b4c,0x30fb2c3d,0x34af32c8,0x357e33eb,0x37773609,0x38723720,0x39573880,0x3a84396b,
0xb835b909,0xb906ba17,0xb577b6e4,0xb66bb813,0xb1a2b41e,0xb28db4ce,0xa4f5ae37,0xa5bfaf36,0x305d2b72,0x31112c50,0x34c932ec,0x35993408,0x37a4362b,0x388a3744,0x397a389c,0x3aad398a,
0xb84eb929,0xb922ba3b,0xb595b70b,0xb68ab828,0xb1c0b433,0xb2aab4e4,0xa50fae57,0xa5d8af55,0x30742b98,0x31282c63,0x34e23310,0x35b3341a,0x37d0364d,0x38a23768,0x399e38b9,0x3ad739aa,
0xb868b949,0xb93eba60,0xb5b3b733,0xb6a9b83d,0xb1ddb449,0xb2c8b4fa,0xa528ae77,0xa5f1af75,0x308a2bbe,0x313e2c76,0x34fc3335,0x35ce342d,0x37fd3670,0x38ba378c,0x39c338d6,0x3b0239ca,
0xb881b96a,0xb95aba86,0xb5d2b75b,0xb6c8b852,0xb1fab45f,0xb2e5b511,0xa541ae97,0xa60aaf95,0x30a12be3,0x31552c89,0x35163359,0x35e9343f,0x38153693,0x38d237b1,0x39e838f3,0x3b2d39eb,
0xb89bb98c,0xb977baac,0xb5f0b783,0xb6e8b868,0xb217b475,0xb303b527,0xa55aaeb6,0xa623afb5,0x30b72c05,0x316b2c9c,0x3530337d,0x36043452,0x382c36b6,0x38eb37d6,0x3a0e3910,0x3b593a0c,
0xb8b6b9ae,0xb994bad3,0xb60eb7ab,0xb708b87d,0xb235b48b,0xb321b53e,0xa573aed6,0xa63cafd5,0x30ce2c18,0x31822caf,0x354a33a2,0x361e3464,0x384336d9,0x390437fb,0x3a35392e,0x3b873a2d,
0x214d2216,0x319b326c,0x1f762084,0x2fe830c8,0x1c521de4,0x2c962e40,0x14b6197f,0x250229d7,0x97db8e48,0xa82c9ead,0x9d1b9b12,0xad6bab82,0xa0209ead,0xb05eaf14,0xa1b2a0e9,0xb204b131,
0x27f32890,0x3241332b,0x259826c6,0x306a3156,0x227b246b,0x2d202efb,0x1b122020,0x25982a87,0x9de494b6,0xa8aa9f76,0xa3a8a14d,0xae0eac32,0xa62fa502,0xb0e1afe8,0xa845a75d,0xb2b6b1cc,
0x2aa02b9b,0x32e733e8,0x28aa29a5,0x30e131e5,0x2566275d,0x2daa2fb6,0x1de422df,0x262f2b36,0xa0e997db,0xa927a020,0xa661a46b,0xaeb0aca2,0xa927a82c,0xb163b05e,0xab1daa22,0xb368b266,
0x2ca22d52,0x338d3452,0x2a872be6,0x31563273,0x278f2927,0x2e333039,0x202024cf,0x26c62be6,0xa2df997f,0xa9a5a084,0xa877a62f,0xaf53ad13,0xab36a9d7,0xb1e5b0c8,0xacfaac4b,0xb40cb300,
0x2df52ed6,0x341834b0,0x2c322d13,0x31cc3300,0x28dc2aa0,0x2ebd3096,0x214d262f,0x275d2c4b,0xa46b9b12,0xaa22a0e9,0xa9bea7f3,0xaff5ad84,0xaca2ab82,0xb266b131,0xae65ad84,0xb464b399,
0x2f46302c,0x346a350c,0x2d202e33,0x3241338d,0x29f02c0c,0x2f4630f3,0x227b278f,0x27f32ca2,0xa5669c52,0xaaa0a14d,0xab04a8dc,0xb04badf5,0xadaaac96,0xb2e7b19b,0xafcfaebd,0xb4bcb418,
0x304b30ed,0x34bc3568,0x2e0e2f53,0x32b6340c,0x2b042cc8,0x2fcf3150,0x23a82877,0x28452cfa,0xa6619d1b,0xab1da1b2,0xac25a9be,0xb09cae65,0xaeb0ad6b,0xb368b204,0xb09caff5,0xb512b464,
0x30f331ad,0x350c35c4,0x2efb3039,0x332b3452,0x2c0c2d84,0x302c31ad,0x246b2927,0x28902d52,0xa75d9de4,0xab9ba216,0xacc8aaa0,0xb0edaed6,0xafb6ae40,0xb3e8b26c,0xb150b096,0xb568b4b0,
0x355d361e,0x37c63867,0x339f3497,0x359836b4,0x3071320a,0x32913473,0x28dc2daa,0x2b363032,0xac0ca27b,0xae01a4cf,0xb13eaf46,0xb3bdb163,0xb434b2d5,0xb627b506,0xb5beb4fa,0xb826b73e,
0x35ac3678,0x3808388f,0x340934dd,0x35cf36f5,0x30b53266,0x32d534a0,0x29272e01,0x2b82305e,0xac4ba2df,0xae40a502,0xb18eafb6,0xb406b19b,0xb473b33d,0xb663b539,0xb612b545,0xb84cb784,
0x35fb36d0,0x382c38b7,0x34433521,0x36073736,0x30f932c2,0x331834ce,0x29722e59,0x2bcd308a,0xac89a344,0xae7ea534,0xb1dfb013,0xb42eb1d2,0xb4b3b3a5,0xb6a0b56b,0xb666b58f,0xb872b7c9,
0x36493728,0x385038de,0x347c3565,0x363e3776,0x313e331e,0x335c34fa,0x29be2eb0,0x2c0c30b5,0xacc8a3a8,0xaebda566,0xb22fb04b,0xb455b20a,0xb4f1b406,0xb6dcb59d,0xb6b9b5d8,0xb898b807,
0x3697377e,0x38743904,0x34b635a9,0x367537b6,0x3182337a,0x339f3527,0x2a092f08,0x2c3230e1,0xad07a406,0xaefba598,0xb27fb083,0xb47cb241,0xb530b43a,0xb717b5cf,0xb70cb621,0xb8bdb828,
0x36e437d4,0x3897392a,0x34ee35ed,0x36ab37f5,0x31c633d6,0x33e23554,0x2a542f5f,0x2c57310c,0xad45a439,0xaf3aa5cb,0xb2cfb0bb,0xb4a4b279,0xb56eb46d,0xb752b601,0xb75db669,0xb8e1b84a,
0x37303814,0x38b9394e,0x3527362f,0x36e1381a,0x320a3418,0x34123580,0x2aa02fb6,0x2c7d3137,0xad84a46b,0xaf78a5fd,0xb31eb0f3,0xb4cbb2b0,0xb5acb4a0,0xb78cb632,0xb7adb6b1,0xb905b86b,
0x377c383e,0x38db3972,0x355f3672,0x37173838,0x324e3446,0x343435ac,0x2aeb3007,0x2ca23163,0xadc3a49d,0xafb6a62f,0xb36eb12b,0xb4f1b2e7,0xb5eab4d4,0xb7c6b663,0xb7fdb6f8,0xb928b88b,
0x38fd3996,0x39f33a91,0x374c3857,0x3874393e,0x345535d8,0x355d3730,0x2cc8318e,0x2df532e7,0xaff5a661,0xb0f3a7f3,0xb518b31e,0xb649b46a,0xb800b694,0xb8dbb808,0xb94bb8ab,0xba45b99b,
0x391e39b8,0x3a0f3aad,0x37813875,0x388c3959,0x34763604,0x357d375a,0x2cee31b9,0x2e1a3312,0xb01aa694,0xb112a813,0xb53fb356,0xb66fb485,0xb81cb6c5,0xb8f5b81f,0xb96db8cb,0xba61b9b7,
0x393e39da,0x3a2b3ac7,0x37b63893,0x38a53974,0x3497362f,0x359d3784,0x2d1331e5,0x2e40333d,0xb039a6c6,0xb131a82c,0xb565b38d,0xb694b4a0,0xb838b6f5,0xb90fb836,0xb98eb8ea,0xba7cb9d2,
0x395e39fb,0x3a453ae0,0x37ea38b0,0x38bd398e,0x34b9365b,0x35be37ad,0x2d393210,0x2e653368,0xb058a6f8,0xb150a845,0xb58cb3c3,0xb6b9b4bc,0xb854b725,0xb928b84c,0xb9aeb909,0xba97b9ed,
0x397d3a1b,0x3a5f3af9,0x380f38cd,0x38d539a8,0x34da3686,0x35de37d7,0x2d5e323b,0x2e8b3393,0xb077a72a,0xb16fa85e,0xb5b2b3fa,0xb6deb4d7,0xb870b755,0xb941b863,0xb9ceb927,0xbab0ba07,
0x399b3a3a,0x3a793b10,0x382838ea,0x38ed39c1,0x34fa36b1,0x35fe3800,0x2d843266,0x2eb033bd,0xb096a75d,0xb18ea877,0xb5d8b418,0xb703b4f1,0xb88bb784,0xb95ab879,0xb9edb945,0xbac9ba21,
0x39b93a58,0x3a913b26,0x38423906,0x390439da,0x351b36dc,0x361e3814,0x2daa3291,0x2ed633e8,0xb0b5a78f,0xb1ada890,0xb5feb434,0xb728b50c,0xb8a6b7b3,0xb972b88f,0xba0bb962,0xbae0ba3a,
0x39d73a75,0x3aa93b3c,0x385b3922,0x391b39f2,0x353c3706,0x363e3828,0x2dcf32bc,0x2efb3409,0xb0d4a7c1,0xb1cca8aa,0xb624b44f,0xb74cb527,0xb8c1b7e2,0xb98ab8a5,0xba29b97f,0xbaf7ba52,
0x3ac03b50,0x3b5e3bcb,0x39323a0a,0x39de3ab8,0x365e383c,0x375738d7,0x2f21341f,0x302634c8,0xb1eba8c3,0xb2e1a98c,0xb770b542,0xb846b615,0xb9a2b8bb,0xba51b960,0xbb0dba6a,0xbb9cbb11,
0x3ad73b63,0x3b6e3bd6,0x39493a22,0x39f23acb,0x367d3850,0x377638ea,0x2f463434,0x303934dd,0xb20aa8dc,0xb300a9a5,0xb795b55d,0xb857b62f,0xb9b9b8d0,0xba65b974,0xbb22ba81,0xbba9bb24,
0x3aec3b75,0x3b7d3bdf,0x395f3a39,0x3a063ade,0x369d3864,0x379538fd,0x2f6c3449,0x304b34f1,0xb229a8f5,0xb31ea9be,0xb7b8b577,0xb868b649,0xb9d0b8e5,0xba79b987,0xbb36ba97,0xbbb6bb35,
0x3b013b86,0x3b8c3be7,0x39753a4f,0x3a193af0,0x36bc3878,0x37b3390f,0x2f91345e,0x305e3506,0xb247a90e,0xb33da9d7,0xb7dcb592,0xb879b663,0xb9e7b8fa,0xba8cb99a,0xbb4abaad,0xbbc2bb46,
0x3b153b96,0x3b993bee,0x398a3a65,0x3a2d3b02,0x36dc388b,0x37d13921,0x2fb63473,0x3071351b,0xb266a927,0xb35ca9f0,0xb800b5ac,0xb88ab67d,0xb9fdb90f,0xba9fb9ad,0xbb5cbac3,0xbbccbb56,
0x3b283ba5,0x3ba63bf4,0x39a03a7a,0x3a3f3b13,0x36fb389e,0x37ef3933,0x2fdc3488,0x30833530,0xb285a940,0xb37aaa09,0xb811b5c7,0xb89bb697,0xba12b924,0xbab1b9c0,0xbb6dbad7,0xbbd6bb65,
0x3b3b3bb3,0x3bb23bf9,0x39b53a8f,0x3a523b24,0x371a38b2,0x38073945,0x3001349d,0x30963545,0xb2a4a959,0xb399aa22,0xb823b5e1,0xb8abb6b1,0xba28b938,0xbac3b9d2,0xbb7ebaeb,0xbbdfbb74,
0x3b4d3bc0,0x3bbd3bfc,0x39ca3aa4,0x3a643b34,0x373938c5,0x38153957,0x301334b3,0x30a9355a,0xb2c2a972,0xb3b7aa3b,0xb834b5fb,0xb8bcb6ca,0xba3cb94c,0xbad4b9e4,0xbb8dbaff,0xbbe6bb82,
0x20e921b2,0x31313204,0x1ead2020,0x2f14305e,0x1b121d1b,0x2b822d6b,0xe4817db,0x1ead282c,0x997f94b6,0xa9d7a502,0x9de49c52,0xae40ac96,0xa0849f76,0xb0c8afe8,0xa216a14d,0xb26cb19b,
0x275d2845,0x31cc32b6,0x2502262f,0x2fe830e1,0x214d23a8,0x2c322e0e,0x14b61de4,0x1f7628aa,0xa0209b12,0xaa87a598,0xa46ba27b,0xaefbad20,0xa6c6a598,0xb156b06a,0xa890a7f3,0xb32bb241,
0x2a222b1d,0x32663368,0x282c2927,0x305e3163,0x246b2661,0x2ca22eb0,0x17db20e9,0x20202927,0xa2df9de4,0xab36a62f,0xa75da566,0xafb6adaa,0xa9a5a8aa,0xb1e5b0e1,0xab9baaa0,0xb3e8b2e7,
0x2c4b2cfa,0x3300340c,0x29d72b36,0x30c831e5,0x262f2877,0x2d132f53,0x197f22df,0x208429a5,0xa4cfa020,0xabe6a6c6,0xa927a78f,0xb039ae33,0xabe6aa87,0xb273b156,0xad52aca2,0xb452b38d,
0x2d842e65,0x33993464,0x2b822ca2,0x31313266,0x27f329be,0x2d842ff5,0x1b12246b,0x20e92a22,0xa62fa14d,0xac4ba75d,0xaaa0a8dc,0xb096aebd,0xad13ac32,0xb300b1cc,0xaed6adf5,0xb4b0b418,
0x2ebd2fcf,0x341834bc,0x2c962daa,0x319b32e7,0x28dc2b04,0x2df5304b,0x1c522566,0x214d2aa0,0xa78fa27b,0xaca2a7f3,0xac0ca9f0,0xb0f3af46,0xae33ad20,0xb38db241,0xb02caf46,0xb50cb46a,
0x2ff5309c,0x34643512,0x2d6b2eb0,0x32043368,0x29be2c25,0x2e65309c,0x1d1b2661,0x21b22b1d,0xa877a3a8,0xacfaa845,0xacc8ab04,0xb150afcf,0xaf53ae0e,0xb40cb2b6,0xb0edb04b,0xb568b4bc,
0x30963150,0x34b03568,0x2e402fb6,0x326c33e8,0x2aa02cc8,0x2ed630ed,0x1de4275d,0x22162b9b,0xa927a46b,0xad52a890,0xad84ac0c,0xb1adb02c,0xb039aefb,0xb452b32b,0xb1adb0f3,0xb5c4b50c,
0x34fa35be,0x373e3826,0x32d53434,0x35063627,0x2f46313e,0x316333bd,0x227b2c0c,0x24cf2e01,0xadaaa8dc,0xb032ab36,0xb20ab071,0xb473b291,0xb497b39f,0xb6b4b598,0xb61eb55d,0xb867b7c6,
0x35453612,0x3784384c,0x333d3473,0x35393663,0x2fb6318e,0x319b3406,0x22df2c4b,0x25022e40,0xae01a927,0xb05eab82,0xb266b0b5,0xb4a0b2d5,0xb4ddb409,0xb6f5b5cf,0xb678b5ac,0xb88fb808,
0x358f3666,0x37c93872,0x33a534b3,0x356b36a0,0x301331df,0x31d2342e,0x23442c89,0x25342e7e,0xae59a972,0xb08aabcd,0xb2c2b0f9,0xb4ceb318,0xb521b443,0xb736b607,0xb6d0b5fb,0xb8b7b82c,
0x35d836b9,0x38073898,0x340634f1,0x359d36dc,0x304b322f,0x320a3455,0x23a82cc8,0x25662ebd,0xaeb0a9be,0xb0b5ac0c,0xb31eb13e,0xb4fab35c,0xb565b47c,0xb776b63e,0xb728b649,0xb8deb850,
0x3621370c,0x382838bd,0x343a3530,0x35cf3717,0x3083327f,0x3241347c,0x24062d07,0x25982efb,0xaf08aa09,0xb0e1ac32,0xb37ab182,0xb527b39f,0xb5a9b4b6,0xb7b6b675,0xb77eb697,0xb904b874,
0x3669375d,0x384a38e1,0x346d356e,0x36013752,0x30bb32cf,0x327934a4,0x24392d45,0x25cb2f3a,0xaf5faa54,0xb10cac57,0xb3d6b1c6,0xb554b3e2,0xb5edb4ee,0xb7f5b6ab,0xb7d4b6e4,0xb92ab897,
0x36b137ad,0x386b3905,0x34a035ac,0x3632378c,0x30f3331e,0x32b034cb,0x246b2d84,0x25fd2f78,0xafb6aaa0,0xb137ac7d,0xb418b20a,0xb580b412,0xb62fb527,0xb81ab6e1,0xb814b730,0xb94eb8b9,
0x36f837fd,0x388b3928,0x34d435ea,0x366337c6,0x312b336e,0x32e734f1,0x249d2dc3,0x262f2fb6,0xb007aaeb,0xb163aca2,0xb446b24e,0xb5acb434,0xb672b55f,0xb838b717,0xb83eb77c,0xb972b8db,
0x38ab394b,0x399b3a45,0x36943800,0x380838db,0x331e3518,0x346a3649,0x26612ff5,0x27f330f3,0xb18eacc8,0xb2e7adf5,0xb5d8b455,0xb730b55d,0xb857b74c,0xb93eb874,0xb996b8fd,0xba91b9f3,
0x38cb396d,0x39b73a61,0x36c5381c,0x381f38f5,0x3356353f,0x3485366f,0x2694301a,0x28133112,0xb1b9acee,0xb312ae1a,0xb604b476,0xb75ab57d,0xb875b781,0xb959b88c,0xb9b8b91e,0xbaadba0f,
0x38ea398e,0x39d23a7c,0x36f53838,0x3836390f,0x338d3565,0x34a03694,0x26c63039,0x282c3131,0xb1e5ad13,0xb33dae40,0xb62fb497,0xb784b59d,0xb893b7b6,0xb974b8a5,0xb9dab93e,0xbac7ba2b,
0x390939ae,0x39ed3a97,0x37253854,0x384c3928,0x33c3358c,0x34bc36b9,0x26f83058,0x28453150,0xb210ad39,0xb368ae65,0xb65bb4b9,0xb7adb5be,0xb8b0b7ea,0xb98eb8bd,0xb9fbb95e,0xbae0ba45,
0x392739ce,0x3a073ab0,0x37553870,0x38633941,0x33fa35b2,0x34d736de,0x272a3077,0x285e316f,0xb23bad5e,0xb393ae8b,0xb686b4da,0xb7d7b5de,0xb8cdb80f,0xb9a8b8d5,0xba1bb97d,0xbaf9ba5f,
0x394539ed,0x3a213ac9,0x3784388b,0x3879395a,0x341835d8,0x34f13703,0x275d3096,0x2877318e,0xb266ad84,0xb3bdaeb0,0xb6b1b4fa,0xb800b5fe,0xb8eab828,0xb9c1b8ed,0xba3ab99b,0xbb10ba79,
0x39623a0b,0x3a3a3ae0,0x37b338a6,0x388f3972,0x343435fe,0x350c3728,0x278f30b5,0x289031ad,0xb291adaa,0xb3e8aed6,0xb6dcb51b,0xb814b61e,0xb906b842,0xb9dab904,0xba58b9b9,0xbb26ba91,
0x397f3a29,0x3a523af7,0x37e238c1,0x38a5398a,0x344f3624,0x3527374c,0x27c130d4,0x28aa31cc,0xb2bcadcf,0xb409aefb,0xb706b53c,0xb828b63e,0xb922b85b,0xb9f2b91b,0xba75b9d7,0xbb3cbaa9,
0x3a6a3b0d,0x3b113b9c,0x38bb39a2,0x39603a51,0x35423770,0x36153846,0x28c331eb,0x298c32e1,0xb41faf21,0xb4c8b026,0xb83cb65e,0xb8d7b757,0xba0ab932,0xbab8b9de,0xbb50bac0,0xbbcbbb5e,
0x3a813b22,0x3b243ba9,0x38d039b9,0x39743a65,0x355d3795,0x362f3857,0x28dc320a,0x29a53300,0xb434af46,0xb4ddb039,0xb850b67d,0xb8eab776,0xba22b949,0xbacbb9f2,0xbb63bad7,0xbbd6bb6e,
0x3a973b36,0x3b353bb6,0x38e539d0,0x39873a79,0x357737b8,0x36493868,0x28f53229,0x29be331e,0xb449af6c,0xb4f1b04b,0xb864b69d,0xb8fdb795,0xba39b95f,0xbadeba06,0xbb75baec,0xbbdfbb7d,
0x3aad3b4a,0x3b463bc2,0x38fa39e7,0x399a3a8c,0x359237dc,0x36633879,0x290e3247,0x29d7333d,0xb45eaf91,0xb506b05e,0xb878b6bc,0xb90fb7b3,0xba4fb975,0xbaf0ba19,0xbb86bb01,0xbbe7bb8c,
0x3ac33b5c,0x3b563bcc,0x390f39fd,0x39ad3a9f,0x35ac3800,0x367d388a,0x29273266,0x29f0335c,0xb473afb6,0xb51bb071,0xb88bb6dc,0xb921b7d1,0xba65b98a,0xbb02ba2d,0xbb96bb15,0xbbeebb99,
0x3ad73b6d,0x3b653bd6,0x39243a12,0x39c03ab1,0x35c73811,0x3697389b,0x29403285,0x2a09337a,0xb488afdc,0xb530b083,0xb89eb6fb,0xb933b7ef,0xba7ab9a0,0xbb13ba3f,0xbba5bb28,0xbbf4bba6,
0x3aeb3b7e,0x3b743bdf,0x39383a28,0x39d23ac3,0x35e13823,0x36b138ab,0x295932a4,0x2a223399,0xb49db001,0xb545b096,0xb8b2b71a,0xb945b807,0xba8fb9b5,0xbb24ba52,0xbbb3bb3b,0xbbf9bbb2,
0x3aff3b8d,0x3b823be6,0x394c3a3c,0x39e43ad4,0x35fb3834,0x36ca38bc,0x297232c2,0x2a3b33b7,0xb4b3b013,0xb55ab0a9,0xb8c5b739,0xb957b815,0xbaa4b9ca,0xbb34ba64,0xbbc0bb4d,0xbbfcbbbd,
0x39b839ba,0x3a973ab5,0x39b339b5,0x3a583a78,0x39af39b1,0x3a153a37,0x39aa39ad,0x39cd39f2,0x39a639a8,0x398239a8,0x39a139a4,0x3933395b,0x399d399f,0x38e03909,0x3999399b,0x388938b5,
0xb979b972,0xb865b832,0xb986b980,0xb8c7b896,0xb994b98d,0xb924b8f6,0xb9a1b99b,0xb97db951,0xb9afb9a8,0xb9d2b9a8,0xb9bcb9b5,0xba21b9fa,0xb9c9b9c3,0xba6bba47,0xb9d6b9d0,0xbab0ba8e,
0xb9f4b9fe,0xbac7bae9,0xb9dfb9e9,0xba7ebaa3,0xb9c9b9d4,0xba2dba56,0xb9b3b9be,0xb9d6ba02,0xb99db9a8,0xb979b9a8,0xb986b992,0xb916b948,0xb970b97b,0xb8adb8e2,0xb958b964,0xb840b877,
0x39373927,0x381a37b7,0x39583948,0x38943858,0x39793969,0x390738ce,0x39993989,0x3974393e,0x39b839a8,0x39da39a8,0x39d639c7,0x3a393a0b,0x39f439e5,0x3a903a65,0x3a113a02,0x3ade3ab8,
0x3a2d3a3f,0x3af43b1a,0x3a093a1b,0x3aa23acc,0x39e339f6,0x3a453a74,0x39bc39d0,0x39df3a13,0x399439a8,0x397039a8,0x396b3980,0x38f83935,0x39413956,0x387a38ba,0x3916392b,0x37e83838,
0xb8f3b8d8,0xb79bb705,0xb929b90e,0xb85fb817,0xb95db943,0xb8eab8a6,0xb990b976,0xb96bb92b,0xb9c0b9a8,0xb9e3b9a8,0xb9f0b9d8,0xba50ba1b,0xba1dba07,0xbab3ba83,0xba49ba33,0xbb0abae0,
0xba64ba7c,0xbb1ebb46,0xba31ba4b,0xbac4baf3,0xb9fcba17,0xba5cba92,0xb9c5b9e1,0xb9e7ba23,0xb98bb9a8,0xb966b9a8,0xb94fb96d,0xb8dbb922,0xb911b930,0xb845b891,0xb8d1b8f1,0xb74eb7ee,
0x38ad3887,0x36ff364e,0x38f838d3,0x382a37ac,0x3941391d,0x38cc387c,0x39863964,0x39623918,0x39c939a8,0x39eb39a8,0x3a0939e9,0x3a673a2b,0x3a453a27,0x3ad53aa0,0x3a7e3a62,0x3b323b05,
0x3b453b6e,0x3bbc3bdd,0x3ae53b17,0x3b573b8f,0x3a733aae,0x3ac73b14,0x39f03a33,0x3a113a71,0x395d39a8,0x393739a8,0x38bc390e,0x384038bf,0x380f3867,0x365f3775,0x36af376a,0x341a3540,
0xb65fb593,0xb389b115,0xb7e8b726,0xb625b4f9,0xb8adb852,0xb830b748,0xb958b905,0xb933b8b5,0xb9f4b9a8,0xba15b9a8,0xba7eba3b,0xbad1ba78,0xbaf4babc,0xbb63bb20,0xbb57bb28,0xbbc6bb9b,
0xbb68bb91,0xbbd0bbed,0xbb04bb39,0xbb6fbba6,0xba89bac9,0xbadbbb2b,0xb9f8ba43,0xba19ba7f,0xb954b9a8,0xb92eb9a8,0xb89eb8fb,0xb820b8ab,0xb7b2b83d,0xb5ebb71b,0xb60eb6e3,0xb2deb4b1,
0x35bc34d5,0x32322f0e,0x377a369e,0x35b13469,0x388e3828,0x380f36ee,0x394f38f1,0x392938a0,0x39fc39a8,0x3a1d39a8,0x3a933a4b,0x3ae53a87,0x3b133ad6,0x3b7a3b36,0x3b783b49,0x3bd93bb1,
0x3b873baf,0x3be13bf8,0x3b213b58,0x3b853bbb,0x3a9e3ae3,0x3aee3b41,0x3a003a52,0x3a213a8e,0x394a39a8,0x392439a8,0x387f38e7,0x37fe3896,0x37423812,0x357636c1,0x356a3659,0x31853420,
0xb517b414,0xb0d7abd9,0xb70ab614,0xb53ab3ae,0xb86fb7f9,0xb7ddb693,0xb946b8dd,0xb91fb88c,0xba04b9a8,0xba25b9a8,0xbaa9ba5a,0xbaf7ba95,0xbb2fbaf0,0xbb90bb4b,0xbb96bb67,0xbbe8bbc4,
0xbba3bbc9,0xbbefbbff,0xbb3dbb74,0xbb9abbcd,0xbab3bafc,0xbb01bb55,0xba09ba62,0xba29ba9c,0xb941b9a8,0xb91bb9a8,0xb85fb8d3,0xb7bdb881,0xb6d2b7cd,0xb4ffb665,0xb4c3b5ce,0xb029b31b,
0x346f32a1,0x2ef52248,0x36993587,0x34c33288,0x385037a1,0x379b3637,0x393c38c9,0x39163877,0x3a0d39a8,0x3a2d39a8,0x3abd3a69,0x3b0a3aa3,0x3b4a3b08,0x3ba33b5f,0x3bb03b82,0x3bf43bd5,
0x3bf83c00,0x3bf93bd4,0x3bac3bdc,0x3be43bfe,0x3b133b69,0x3b543bab,0x3a313aaa,0x3a503ae0,0x391139a8,0x38ea39a8,0x377a386d,0x366b3817,0x34873608,0x313b348d,0x2d9731f4,0xad65291b,
0xac3828b6,0x2ec33365,0xb44bb160,0xb0bea57f,0xb759b5da,0xb648b45d,0xb90cb862,0xb8e5b80d,0xba35b9a8,0xba54b9a8,0xbb1bbab1,0xbb5cbae6,0xbbb5bb72,0xbbe9bbb2,0xbbfcbbe3,0xbbf5bc00,
0xbbfebbfc,0xbbefbbbc,0xbbbdbbe9,0xbbeebc00,0xbb24bb7b,0xbb63bbb9,0xba39bab8,0xba58baed,0xb907b9a8,0xb8e0b9a8,0xb737b858,0xb625b802,0xb40eb5ab,0xb042b42c,0xa9b1b0cb,0x30109a48,
0x25e4ad7e,0xb0beb475,0x33a23036,0x2f8ba3db,0x3715357c,0x360233f7,0x3902384d,0x38db37ee,0x3a3d39a8,0x3a5c39a8,0x3b2c3abf,0x3b6a3af3,0x3bc53b84,0x3bf23bc0,0x3bff3bee,0x3be93c00,
0x3c003bf4,0x3be23ba0,0x3bcc3bf3,0x3bf53bff,0x3b353b8c,0x3b713bc6,0x3a413ac6,0x3a603af9,0x38fd39a8,0x38d639a8,0x36f43842,0x35df37d8,0x3328354c,0x2e913396,0x16482f40,0xb16ca852,
0x251b304e,0x32193534,0xb2adae14,0xad972aac,0xb6d2b51d,0xb5bcb334,0xb8f8b838,0xb8d1b7c2,0xba45b9a8,0xba64b9a8,0xbb3dbacc,0xbb78baff,0xbbd3bb95,0xbbf8bbcb,0xbc00bbf7,0xbbdabbfd,
0xbbfebbe6,0xbbd2bb80,0xbbd9bbfa,0xbbfbbbfb,0xbb45bb9d,0xbb7fbbd1,0xba49bad3,0xba67bb05,0xb8f3b9a8,0xb8ccb9a8,0xb6afb82d,0xb599b7ac,0xb232b4ed,0xac9cb2d2,0x294dace7,0x32c62c83,
0xac06b1db,0xb371b5f1,0x31b62b75,0x2b43adb0,0x368d34bd,0x3576326f,0x38ee3822,0x38c73796,0x3a4d39a8,0x3a6b39a8,0x3b4c3ad9,0x3b853b0b,0x3bdf3ba4,0x3bfd3bd6,0x3bfc3bfd,0x3bc83bf8,
0x3bbd3b5a,0x3b473a99,0x3bfe3bf4,0x3bf93bbe,0x3b8b3bdb,0x3bb83bf7,0x3a6f3b11,0x3a8c3b3e,0x38c139a8,0x389939a8,0x35523780,0x343236cc,0x294d320d,0xad332de2,0xb40eaedc,0xb6a4b408,
0x346336aa,0x36f438b0,0xa6ad3004,0x2e2d3451,0xb52fb1aa,0xb40ead1a,0xb8bcb76a,0xb894b6b5,0xba73b9a8,0xba90b9a8,0xbb92bb17,0xbbbdbb43,0xbbffbbe0,0xbbf6bbf9,0xbbb2bbf0,0xbb35bbb4,
0xbba5bb30,0xbb21ba5e,0xbc00bbeb,0xbbf3bbaa,0xbb98bbe4,0xbbc2bbfb,0xba76bb1d,0xba93bb49,0xb8b7b9a8,0xb88eb9a8,0xb50bb753,0xb3d3b69e,0xa17fb147,0x2f27ac51,0x34b73099,0x37423499,
0xb50bb75e,0xb790b900,0x9cb6b12e,0xb010b4e1,0x34e730e4,0x33892b11,0x38b2373d,0x38893687,0x3a7a39a8,0x3a9739a8,0x3b9e3b22,0x3bc63b4e,0x3c003be8,0x3bef3bfd,0x3b983be5,0x3b0d3b9e,
0x3b893b02,0x3af73a1f,0x3c003bdf,0x3beb3b93,0x3ba33bec,0x3bcb3bfe,0x3a7e3b28,0x3a9b3b53,0x38ad39a8,0x388439a8,0x34c33726,0x33403670,0xa51b3080,0xb08d297f,0xb55eb1c3,0xb7ddb529,
0x35b13807,0x3815394d,0x28843257,0x31093570,0xb49fb01d,0xb2f7a7da,0xb8a8b710,0xb87fb659,0xba81b9a8,0xba9eb9a8,0xbba9bb2e,0xbbcfbb58,0xbbffbbef,0xbbe6bbff,0xbb7abbd7,0xbae1bb86,
0xbb6abad0,0xbacbb9dc,0xbbfdbbd0,0xbbe1bb79,0xbbaebbf2,0xbbd3bc00,0xba85bb33,0xbaa2bb5d,0xb8a3b9a8,0xb87ab9a8,0xb47bb6f9,0xb2adb642,0x2a7aaf72,0x3185a4b6,0x360232ea,0x383a35b6,
0xb654b85d,0xb85fb996,0xac38b37d,0xb201b5fd,0x34572eaa,0x32631e48,0x389e36e3,0x3874362b,0x3a8939a8,0x3aa539a8,0x3bb33b39,0x3bd73b62,0x3bfc3bf5,0x3bdc3c00,0x3b593bc7,0x3ab33b6b,
0x39b739b9,0x3a883aa6,0x39b239b4,0x3a483a68,0x39ae39b0,0x3a033a26,0x39a939ab,0x39bb39e0,0x39a539a7,0x396e3995,0x39a039a3,0x391e3947,0x399c399e,0x38ca38f5,0x3997399a,0x3873389f,
0xb97cb975,0xb87eb84c,0xb98ab983,0xb8deb8ae,0xb997b991,0xb93bb90d,0xb9a5b99e,0xb993b967,0xb9b2b9ab,0xb9e6b9bd,0xb9bfb9b9,0xba34ba0e,0xb9ccb9c6,0xba7dba59,0xb9d9b9d3,0xbac0ba9f,
0xb9efb9f9,0xbab6bad9,0xb9d9b9e4,0xba6aba91,0xb9c4b9cf,0xba18ba42,0xb9aeb9b9,0xb9bfb9ec,0xb997b9a3,0xb961b991,0xb981b98c,0xb8fcb92f,0xb96ab975,0xb892b8c8,0xb953b95e,0xb824b85c,
0x3940392f,0x383937f6,0x39613950,0x38b13876,0x39813971,0x392338eb,0x39a03991,0x398e395a,0x39bf39b0,0x39f339c1,0x39de39cf,0x3a4f3a22,0x39fb39ec,0x3aa43a7b,0x3a183a0a,0x3af03acb,
0x3a243a36,0x3ae13b07,0x39ff3a12,0x3a8b3ab7,0x39d939ec,0x3a2c3a5d,0x39b239c6,0x39c439f9,0x398a399e,0x3953398c,0x39613975,0x38d93917,0x3936394b,0x3859389a,0x390b3921,0x37a43816,
0xb901b8e6,0xb7e6b750,0xb936b91c,0xb883b83c,0xb96ab950,0xb90bb8c8,0xb99cb983,0xb98ab94b,0xb9ccb9b4,0xb9ffb9c6,0xb9fbb9e4,0xba6aba36,0xba28ba12,0xbacaba9b,0xba53ba3e,0xbb1dbaf5,
0xba57ba70,0xbb09bb33,0xba24ba3e,0xbaabbadc,0xb9efba0a,0xba40ba77,0xb9b7b9d3,0xb9c8ba05,0xb97cb99a,0xb944b988,0xb940b95e,0xb8b6b8fe,0xb901b921,0xb81eb86b,0xb8c0b8e1,0xb6fcb79e,
0x38c0389a,0x375636a7,0x390b38e6,0x38543800,0x3953392f,0x38f238a4,0x39973975,0x3985393d,0x39d939b9,0x3a0c39ca,0x3a1839f9,0x3a843a4a,0x3a533a36,0x3aed3abb,0x3a8b3a70,0x3b473b1c,
0x3b2e3b5a,0x3ba63bce,0x3aca3afe,0x3b373b74,0x3a533a91,0x3a9d3aef,0x39cc3a12,0x39de3a42,0x39363983,0x38fc3971,0x389238e6,0x37fb3880,0x37c5383c,0x35d136eb,0x3651370d,0x330934ae,
0xb6c3b5fa,0xb460b251,0xb824b788,0xb6b8b590,0xb8d9b880,0xb873b7d5,0xb981b92f,0xb96eb8f5,0xba18b9cf,0xba48b9e0,0xba9dba5d,0xbafabaa6,0xbb0fbad9,0xbb80bb43,0xbb6cbb40,0xbbd8bbb2,
0xbb51bb7d,0xbbbdbbe0,0xbae7bb1f,0xbb4ebb8c,0xba66baa9,0xbaafbb04,0xb9d1ba1e,0xb9e2ba4e,0xb928b97e,0xb8edb96c,0xb86eb8cd,0xb7afb866,0xb74bb80b,0xb54fb684,0xb5a2b679,0xb197b411,
0x362e3549,0x338330de,0x37e6370d,0x3651350e,0x38c0385c,0x38593788,0x397c3921,0x396a38e6,0x3a2439d3,0x3a5339e4,0x3ab63a70,0x3b0f3ab7,0x3b2e3af5,0x3b973b5a,0x3b8d3b61,0x3be83bc7,
0x3b703b9c,0x3bd03bef,0x3b033b3d,0x3b653ba2,0x3a793ac1,0x3ac03b19,0x39d53a2a,0x39e63a59,0x3919397a,0x38de3967,0x384938b4,0x3761384c,0x36cf37b4,0x34cc361d,0x34f035e2,0x302332e4,
0xb596b496,0xb244aecf,0xb783b690,0xb5e8b48a,0xb8a7b836,0xb83eb73a,0xb978b912,0xb965b8d7,0xba30b9d7,0xba5fb9e8,0xbacdba82,0xbb23bac8,0xbb4cbb10,0xbbacbb6f,0xbbaabb7f,0xbbf4bbd8,
0xbb8dbbb7,0xbbe0bbf9,0xbb1dbb5a,0xbb7abbb5,0xba8bbad9,0xbad0bb2d,0xb9d9ba36,0xb9eaba65,0xb90bb975,0xb8cfb963,0xb824b89a,0xb713b831,0xb651b750,0xb447b5b3,0xb43bb549,0xad58b1a4,
0x34fc33c0,0x31032bc0,0x371e3611,0x357e3405,0x388d3811,0x382436eb,0x39733903,0x396138c8,0x3a3c39db,0x3a6a39ec,0x3ae43a94,0x3b373ad9,0x3b673b2a,0x3bbe3b83,0x3bc33b9a,0x3bfc3be7,
0x3bed3bff,0x3bff3bea,0x3b8d3bc7,0x3bcc3bf5,0x3ae13b40,0x3b1d3b83,0x39ef3a70,0x39ff3a9b,0x38c0395e,0x3883394b,0x36c33816,0x357e3750,0x33833549,0x2e84332e,0x28cf3061,0xb0aca5b2,
0xaf7ea376,0x29663166,0xb514b2fd,0xb2bfad71,0xb809b69b,0xb734b555,0xb95cb8b9,0xb949b87b,0xba75b9f1,0xbaa1ba01,0xbb49bae9,0xbb8bbb25,0xbbcfbb96,0xbbf9bbd2,0xbc00bbf2,0xbbe3bbfe,
0xbbf6bc00,0xbbfcbbda,0xbb9fbbd6,0xbbd8bbfb,0xbaf0bb52,0xbb2cbb92,0xb9f3ba7b,0xba03baa6,0xb8b1b95a,0xb873b947,0xb673b7f6,0xb52cb718,0xb276b4de,0xac5eb251,0x2052ae39,0x321f2bf2,
0x2cf4a806,0xad3fb2d8,0x34a831ee,0x31e22a93,0x37db364b,0x36fc3502,0x395738a9,0x3944386b,0x3a8039f5,0x3aab3a05,0x3b5b3af8,0x3b993b33,0x3bdd3ba7,0x3bfd3bdd,0x3bff3bfa,0x3bd13bf9,
0x3bfd3bfd,0x3bf53bc6,0x3baf3be3,0x3be23bff,0x3b003b64,0x3b393ba0,0x39f73a86,0x3a083ab0,0x38a23955,0x38633942,0x362237bf,0x34d836e0,0x31663472,0x286b3172,0xaaf82b5c,0xb390ae84,
0xa8cf2cf4,0x2fc93423,0xb43bb0de,0xb103a484,0xb7a4b5fa,0xb6c3b4ae,0xb953b89a,0xb940b85c,0xba8bb9f9,0xbab6ba0a,0xbb6cbb07,0xbba6bb40,0xbbe8bbb7,0xbc00bbe7,0xbbfabbff,0xbbbabbf1,
0xbc00bbf6,0xbbebbbae,0xbbbebbed,0xbbebbc00,0xbb0fbb74,0xbb47bbad,0xb9fbba91,0xba0cbabb,0xb892b950,0xb854b93d,0xb5d1b788,0xb484b6a7,0xb055b405,0x9248b093,0x2e6ba484,0x347e3086,
0x98b6afe2,0xb128b4d8,0x339c2f97,0x3023a420,0x376c35a8,0x368a345a,0x394e388b,0x393b384c,0x3a9639fd,0x3ac03a0e,0x3b7c3b16,0x3bb33b4d,0x3bf23bc5,0x3c003bef,0x3bf03c00,0x3ba03be5,
0x3bde3b91,0x3b8a3af7,0x3bf23bff,0x3c003be3,0x3b533bb9,0x3b823bdf,0x3a103ac5,0x3a203aec,0x38443939,0x38033925,0x342f366d,0x31b03584,0xa8392f65,0xb15a1d7f,0xb531b1c9,0xb7e0b55b,
0x3269358a,0x35a83819,0xae842a61,0x205231e2,0xb651b405,0xb567b15a,0xb936b83c,0xb923b7f6,0xbacaba12,0xbaf0ba22,0xbbbebb5a,0xbbe3bb88,0xbbfdbbf5,0xbbddbc00,0xbb81bbd6,0xbadfbb7c,
0xbbcebb70,0xbb6dbac6,0xbbf8bbfb,0xbbffbbd6,0xbb60bbc4,0xbb8dbbe7,0xba14bacf,0xba24baf5,0xb834b934,0xb7e6b921,0xb3b4b634,0xb103b549,0x2c44ada3,0x326925b2,0x35e23309,0x384135f4,
0xb3a8b63a,0xb63fb869,0x2cc2ad58,0xa89db2f0,0x3617335f,0x352c30ac,0x3931382c,0x391e37d5,0x3ad43a16,0x3afa3a26,0x3bc93b66,0x3bea3b92,0x3bf93bfa,0x3bcf3bff,0x3b5f3bc5,0x3aad3b5d,
0x3bba3b4c,0x3b4d3a93,0x3bfc3bf6,0x3bfd3bc7,0x3b6c3bce,0x3b973bed,0x3a183ad9,0x3a283afe,0x3824392f,0x37c5391c,0x330935fa,0x3055350e,0xae6b2bc0,0xb377aa61,0xb690b423,0xb890b68a,
0x347236e5,0x36d438b6,0xa9fd2f7e,0x2c1233fd,0xb5dcb2b3,0xb4f0affb,0xb92db81c,0xb919b7b4,0xbaddba1a,0xbb03ba2a,0xbbd3bb72,0xbbf0bb9c,0xbbf2bbfe,0xbbbfbbfc,0xbb38bbaf,0xba77bb3c,
0xbba4bb23,0xbb2aba5b,0xbbffbbee,0xbbfabbb6,0xbb77bbd7,0xbba1bbf3,0xba1cbae2,0xba2cbb07,0xb813b92a,0xb7a4b917,0xb25db5bf,0xaf4cb4d2,0x3048a839,0x34412cf4,0x373a34c0,0x38dc371e,
0xb50eb78e,0xb767b901,0x24e9b0d1,0xadd5b484,0x35a23207,0x34b42e9d,0x3928380b,0x39143793,0x3ae73a1e,0x3b0c3a2e,0x3bdb3b7d,0x3bf53ba6,0x3be93c00,0x3bad3bf7,0x3b0d3b97,0x3a3e3b18,
0xb999b996,0xb889b85d,0xb99db99b,0xb8e0b8b5,0xb9a1b99f,0xb933b909,0xb9a6b9a4,0xb982b95b,0xb9aab9a8,0xb9cdb9a8,0xb9afb9ad,0xba15b9f2,0xb9b3b9b1,0xba58ba37,0xb9b8b9b5,0xba97ba78,
0xb9d6b9dc,0xbab0bad0,0xb9c9b9d0,0xba6bba8e,0xb9bcb9c3,0xba21ba47,0xb9afb9b5,0xb9d2b9fa,0xb9a1b9a8,0xb97db9a8,0xb994b99b,0xb924b951,0xb986b98d,0xb8c7b8f6,0xb979b980,0xb865b896,
0x3958394d,0x38403807,0x39703964,0x38ad3877,0x3986397b,0x391638e2,0x399d3992,0x39793948,0x39b339a8,0x39d639a8,0x39c939be,0x3a2d3a02,0x39df39d4,0x3a7e3a56,0x39f439e9,0x3ac73aa3,
0x3a113a1f,0x3ade3b02,0x39f43a02,0x3a903ab8,0x39d639e5,0x3a393a65,0x39b839c7,0x39da3a0b,0x399939a8,0x397439a8,0x39793989,0x3907393e,0x39583969,0x389438ce,0x39373948,0x381a3858,
0xb916b900,0xb7e8b75e,0xb941b92b,0xb87ab838,0xb96bb956,0xb8f8b8ba,0xb994b980,0xb970b935,0xb9bcb9a8,0xb9dfb9a8,0xb9e3b9d0,0xba45ba13,0xba09b9f6,0xbaa2ba74,0xba2dba1b,0xbaf4bacc,
0xba49ba5e,0xbb0abb30,0xba1dba33,0xbab3bae0,0xb9f0ba07,0xba50ba83,0xb9c0b9d8,0xb9e3ba1b,0xb990b9a8,0xb96bb9a8,0xb95db976,0xb8eab92b,0xb929b943,0xb85fb8a6,0xb8f3b90e,0xb79bb817,
0x38d138b0,0x374e36aa,0x391138f1,0x384537ee,0x394f3930,0x38db3891,0x398b396d,0x39663922,0x39c539a8,0x39e739a8,0x39fc39e1,0x3a5c3a23,0x3a313a17,0x3ac43a92,0x3a643a4b,0x3b1e3af3,
0x3a7e3a99,0x3b323b5a,0x3a453a62,0x3ad53b05,0x3a093a27,0x3a673aa0,0x39c939e9,0x39eb3a2b,0x398639a8,0x396239a8,0x39413964,0x38cc3918,0x38f8391d,0x382a387c,0x38ad38d3,0x36ff37ac,
0xb6afb5f1,0xb41ab1db,0xb80fb76a,0xb65fb540,0xb8bcb867,0xb840b775,0xb95db90e,0xb937b8bf,0xb9f0b9a8,0xba11b9a8,0xba73ba33,0xbac7ba71,0xbae5baae,0xbb57bb14,0xbb45bb17,0xbbbcbb8f,
0xbb57bb80,0xbbc6bbe6,0xbaf4bb28,0xbb63bb9b,0xba7ebabc,0xbad1bb20,0xb9f4ba3b,0xba15ba78,0xb958b9a8,0xb933b9a8,0xb8adb905,0xb830b8b5,0xb7e8b852,0xb625b748,0xb65fb726,0xb389b4f9,
0x360e3534,0x32de304e,0x37b236e3,0x35eb34b1,0x389e383d,0x3820371b,0x395438fb,0x392e38ab,0x39f839a8,0x3a1939a8,0x3a893a43,0x3adb3a7f,0x3b043ac9,0x3b6f3b2b,0x3b683b39,0x3bd03ba6,
0x3b783ba0,0x3bd93bf4,0x3b133b49,0x3b7a3bb1,0x3a933ad6,0x3ae53b36,0x39fc3a4b,0x3a1d3a87,0x394f39a8,0x392939a8,0x388e38f1,0x380f38a0,0x377a3828,0x35b136ee,0x35bc369e,0x32323469,
0xb56ab475,0xb185ad7e,0xb742b659,0xb576b420,0xb87fb812,0xb7feb6c1,0xb94ab8e7,0xb924b896,0xba00b9a8,0xba21b9a8,0xba9eba52,0xbaeeba8e,0xbb21bae3,0xbb85bb41,0xbb87bb58,0xbbe1bbbb,
0xbb96bbbc,0xbbe8bbfc,0xbb2fbb67,0xbb90bbc4,0xbaa9baf0,0xbaf7bb4b,0xba04ba5a,0xba25ba95,0xb946b9a8,0xb91fb9a8,0xb86fb8dd,0xb7ddb88c,0xb70ab7f9,0xb53ab693,0xb517b614,0xb0d7b3ae,
0x34c33365,0x302928b6,0x36d235ce,0x34ff331b,0x385f37cd,0x37bd3665,0x394138d3,0x391b3881,0x3a0939a8,0x3a2939a8,0x3ab33a62,0x3b013a9c,0x3b3d3afc,0x3b9a3b55,0x3ba33b74,0x3bef3bcd,
0x3bb03bd4,0x3bf43c00,0x3b4a3b82,0x3ba33bd5,0x3abd3b08,0x3b0a3b5f,0x3a0d3a69,0x3a2d3aa3,0x393c39a8,0x391639a8,0x385038c9,0x379b3877,0x369937a1,0x34c33637,0x346f3587,0x2ef53288,
0xad972248,0x2d6532a1,0xb487b1f4,0xb13ba91b,0xb77ab608,0xb66bb48d,0xb911b86d,0xb8eab817,0xba31b9a8,0xba50b9a8,0xbb13baaa,0xbb54bae0,0xbbacbb69,0xbbe4bbab,0xbbf8bbdc,0xbbf9bbfe,
0xbbfcbbff,0xbbf5bbc9,0xbbb5bbe3,0xbbe9bc00,0xbb1bbb72,0xbb5cbbb2,0xba35bab1,0xba54bae6,0xb90cb9a8,0xb8e5b9a8,0xb759b862,0xb648b80d,0xb44bb5da,0xb0beb45d,0xac38b160,0x2ec3a57f,
0x29b1abd9,0xb010b414,0x340e30cb,0x30421a48,0x373735ab,0x3625342c,0x39073858,0x38e03802,0x3a3939a8,0x3a5839a8,0x3b243ab8,0x3b633aed,0x3bbd3b7b,0x3bee3bb9,0x3bfe3be9,0x3bef3c00,
0x3bff3bf8,0x3be93baf,0x3bc53bee,0x3bf23c00,0x3b2c3b84,0x3b6a3bc0,0x3a3d3abf,0x3a5c3af3,0x390239a8,0x38db39a8,0x3715384d,0x360237ee,0x33a2357c,0x2f8b33f7,0x25e43036,0xb0bea3db,
0x96482f0e,0x316c34d5,0xb328af40,0xae912852,0xb6f4b54c,0xb5dfb396,0xb8fdb842,0xb8d6b7d8,0xba41b9a8,0xba60b9a8,0xbb35bac6,0xbb71baf9,0xbbccbb8c,0xbbf5bbc6,0xbc00bbf3,0xbbe2bbff,
0xbc00bbed,0xbbdabb91,0xbbd3bbf7,0xbbf8bbfd,0xbb3dbb95,0xbb78bbcb,0xba45bacc,0xba64baff,0xb8f8b9a8,0xb8d1b9a8,0xb6d2b838,0xb5bcb7c2,0xb2adb51d,0xad97b334,0x251bae14,0x32192aac,
0xa94db115,0xb2c6b593,0x32322ce7,0x2c9cac83,0x36af34ed,0x359932d2,0x38f3382d,0x38cc37ac,0x3a4939a8,0x3a6739a8,0x3b453ad3,0x3b7f3b05,0x3bd93b9d,0x3bfb3bd1,0x3bfe3bfa,0x3bd23bfb,
0x3bfc3bdd,0x3bc83b6e,0x3bdf3bfd,0x3bfd3bf8,0x3b4c3ba4,0x3b853bd6,0x3a4d3ad9,0x3a6b3b0b,0x38ee39a8,0x38c739a8,0x368d3822,0x35763796,0x31b634bd,0x2b43326f,0xac062b75,0xb371adb0,
0x340e364e,0x36a43887,0xa94d2edc,0x2d333408,0xb552b20d,0xb432ade2,0xb8c1b780,0xb899b6cc,0xba6fb9a8,0xba8cb9a8,0xbb8bbb11,0xbbb8bb3e,0xbbfebbdb,0xbbf9bbf7,0xbbbdbbf4,0xbb47bbbe,
0xbbb2bb46,0xbb35ba7c,0xbbffbbf0,0xbbf6bbb4,0xbb92bbe0,0xbbbdbbf9,0xba73bb17,0xba90bb43,0xb8bcb9a8,0xb894b9a8,0xb52fb76a,0xb40eb6b5,0xa6adb1aa,0x2e2dad1a,0x34633004,0x36f43451,
0xb4b7b705,0xb742b8d8,0x217fb099,0xaf27b499,0x350b3147,0x33d32c51,0x38b73753,0x388e369e,0x3a7639a8,0x3a9339a8,0x3b983b1d,0x3bc23b49,0x3c003be4,0x3bf33bfb,0x3ba53beb,0x3b213baa,
0x3b983b1a,0x3b0d3a3f,0x3c003be5,0x3bef3b9e,0x3b9e3be8,0x3bc63bfd,0x3a7a3b22,0x3a973b4e,0x38b239a8,0x388939a8,0x34e7373d,0x33893687,0x9cb630e4,0xb0102b11,0xb50bb12e,0xb790b4e1,
0x355e37b7,0x37dd3927,0x251b31c3,0x308d3529,0xb4c3b080,0xb340a97f,0xb8adb726,0xb884b670,0xba7eb9a8,0xba9bb9a8,0xbba3bb28,0xbbcbbb53,0xbc00bbec,0xbbebbbfe,0xbb89bbdf,0xbaf7bb93,
0xbb7abae9,0xbae1b9fe,0xbbffbbd7,0xbbe6bb86,0xbba9bbef,0xbbcfbbff,0xba81bb2e,0xba9ebb58,0xb8a8b9a8,0xb87fb9a8,0xb49fb710,0xb2f7b659,0x2884b01d,0x3109a7da,0x35b13257,0x38153570,
0xb602b832,0xb83ab972,0xaa7ab2ea,0xb185b5b6,0x347b2f72,0x32ad24b6,0x38a336f9,0x387a3642,0x3a8539a8,0x3aa239a8,0x3bae3b33,0x3bd33b5d,0x3bfd3bf2,0x3be13c00,0x3b6a3bd0,0x3acb3b79,
0x3b593ab5,0x3ab339ba,0x3bfc3bc7,0x3bdc3b6b,0x3bb33bf5,0x3bd73c00,0x3a893b39,0x3aa53b62,0x389e39a8,0x387439a8,0x345736e3,0x3263362b,0xac382eaa,0xb2011e48,0xb654b37d,0xb85fb5fd,
0xb99ab997,0xb89fb873,0xb99eb99c,0xb8f5b8ca,0xb9a3b9a0,0xb947b91e,0xb9a7b9a5,0xb995b96e,0xb9abb9a9,0xb9e0b9bb,0xb9b0b9ae,0xba26ba03,0xb9b4b9b2,0xba68ba48,0xb9b9b9b7,0xbaa6ba88,
0xb9d3b9d9,0xba9fbac0,0xb9c6b9cc,0xba59ba7d,0xb9b9b9bf,0xba0eba34,0xb9abb9b2,0xb9bdb9e6,0xb99eb9a5,0xb967b993,0xb991b997,0xb90db93b,0xb983b98a,0xb8aeb8de,0xb975b97c,0xb84cb87e,
0x395e3953,0x385c3824,0x3975396a,0x38c83892,0x398c3981,0x392f38fc,0x39a33997,0x39913961,0x39b939ae,0x39ec39bf,0x39cf39c4,0x3a423a18,0x39e439d9,0x3a913a6a,0x39f939ef,0x3ad93ab6,
0x3a0a3a18,0x3acb3af0,0x39ec39fb,0x3a7b3aa4,0x39cf39de,0x3a223a4f,0x39b039bf,0x39c139f3,0x399139a0,0x395a398e,0x39713981,0x38eb3923,0x39503961,0x387638b1,0x392f3940,0x37f63839,
0xb921b90b,0xb816b7a4,0xb94bb936,0xb89ab859,0xb975b961,0xb917b8d9,0xb99eb98a,0xb98cb953,0xb9c6b9b2,0xb9f9b9c4,0xb9ecb9d9,0xba5dba2c,0xba12b9ff,0xbab7ba8b,0xba36ba24,0xbb07bae1,
0xba3eba53,0xbaf5bb1d,0xba12ba28,0xba9bbaca,0xb9e4b9fb,0xba36ba6a,0xb9b4b9cc,0xb9c6b9ff,0xb983b99c,0xb94bb98a,0xb950b96a,0xb8c8b90b,0xb91cb936,0xb83cb883,0xb8e6b901,0xb750b7e6,
0x38e138c0,0x379e36fc,0x39213901,0x386b381e,0x395e3940,0x38fe38b6,0x399a397c,0x39883944,0x39d339b7,0x3a0539c8,0x3a0a39ef,0x3a773a40,0x3a3e3a24,0x3adc3aab,0x3a703a57,0x3b333b09,
0x3a703a8b,0x3b1c3b47,0x3a363a53,0x3abb3aed,0x39f93a18,0x3a4a3a84,0x39b939d9,0x39ca3a0c,0x39753997,0x393d3985,0x392f3953,0x38a438f2,0x38e6390b,0x38003854,0x389a38c0,0x36a73756,
0xb70db651,0xb4aeb309,0xb83cb7c5,0xb6ebb5d1,0xb8e6b892,0xb880b7fb,0xb983b936,0xb971b8fc,0xba12b9cc,0xba42b9de,0xba91ba53,0xbaefba9d,0xbafebaca,0xbb74bb37,0xbb5abb2e,0xbbcebba6,
0xbb40bb6c,0xbbb2bbd8,0xbad9bb0f,0xbb43bb80,0xba5dba9d,0xbaa6bafa,0xb9cfba18,0xb9e0ba48,0xb92fb981,0xb8f5b96e,0xb880b8d9,0xb7d5b873,0xb788b824,0xb590b6b8,0xb5fab6c3,0xb251b460,
0x367935a2,0x34113197,0x380b374b,0x3684354f,0x38cd386e,0x386637af,0x397e3928,0x396c38ed,0x3a1e39d1,0x3a4e39e2,0x3aa93a66,0x3b043aaf,0x3b1f3ae7,0x3b8c3b4e,0x3b7d3b51,0x3be03bbd,
0x3b613b8d,0x3bc73be8,0x3af53b2e,0x3b5a3b97,0x3a703ab6,0x3ab73b0f,0x39d33a24,0x39e43a53,0x3921397c,0x38e6396a,0x385c38c0,0x37883859,0x370d37e6,0x350e3651,0x3549362e,0x30de3383,
0xb5e2b4f0,0xb2e4b023,0xb7b4b6cf,0xb61db4cc,0xb8b4b849,0xb84cb761,0xb97ab919,0xb967b8de,0xba2ab9d5,0xba59b9e6,0xbac1ba79,0xbb19bac0,0xbb3dbb03,0xbba2bb65,0xbb9cbb70,0xbbefbbd0,
0xbb7fbbaa,0xbbd8bbf4,0xbb10bb4c,0xbb6fbbac,0xba82bacd,0xbac8bb23,0xb9d7ba30,0xb9e8ba5f,0xb912b978,0xb8d7b965,0xb836b8a7,0xb73ab83e,0xb690b783,0xb48ab5e8,0xb496b596,0xaecfb244,
0x3549343b,0x31a42d58,0x37503651,0x35b33447,0x389a3824,0x38313713,0x3975390b,0x396338cf,0x3a3639d9,0x3a6539ea,0x3ad93a8b,0x3b2d3ad0,0x3b5a3b1d,0x3bb53b7a,0x3bb73b8d,0x3bf93be0,
0x3b9a3bc3,0x3be73bfc,0x3b2a3b67,0x3b833bbe,0x3a943ae4,0x3ad93b37,0x39db3a3c,0x39ec3a6a,0x39033973,0x38c83961,0x3811388d,0x36eb3824,0x3611371e,0x3405357e,0x33c034fc,0x2bc03103,
0xb061a8cf,0x25b230ac,0xb549b383,0xb32eae84,0xb816b6c3,0xb750b57e,0xb95eb8c0,0xb94bb883,0xba70b9ef,0xba9bb9ff,0xbb40bae1,0xbb83bb1d,0xbbc7bb8d,0xbbf5bbcc,0xbbffbbed,0xbbeabbff,
0xbbf2bc00,0xbbfebbe3,0xbb96bbcf,0xbbd2bbf9,0xbae9bb49,0xbb25bb8b,0xb9f1ba75,0xba01baa1,0xb8b9b95c,0xb87bb949,0xb69bb809,0xb555b734,0xb2fdb514,0xad71b2bf,0xa376af7e,0x31662966,
0x2e39a052,0xabf2b21f,0x34de3276,0x32512c5e,0x37f63673,0x3718352c,0x395a38b1,0x39473873,0x3a7b39f3,0x3aa63a03,0x3b523af0,0x3b923b2c,0x3bd63b9f,0x3bfb3bd8,0x3c003bf6,0x3bda3bfc,
0x3bfa3bff,0x3bf93bd1,0x3ba73bdd,0x3bdd3bfd,0x3af83b5b,0x3b333b99,0x39f53a80,0x3a053aab,0x38a93957,0x386b3944,0x364b37db,0x350236fc,0x31ee34a8,0x2a9331e2,0xa8062cf4,0xb2d8ad3f,
0xab5c2af8,0x2e843390,0xb472b166,0xb172a86b,0xb7bfb622,0xb6e0b4d8,0xb955b8a2,0xb942b863,0xba86b9f7,0xbab0ba08,0xbb64bb00,0xbba0bb39,0xbbe3bbaf,0xbbffbbe2,0xbbfdbbfd,0xbbc6bbf5,
0xbbffbbfa,0xbbf1bbba,0xbbb7bbe8,0xbbe7bc00,0xbb07bb6c,0xbb40bba6,0xb9f9ba8b,0xba0abab6,0xb89ab953,0xb85cb940,0xb5fab7a4,0xb4aeb6c3,0xb0deb43b,0xa484b103,0x2cf4a8cf,0x34232fc9,
0x2484ae6b,0xb086b47e,0x34053055,0x30931248,0x378835d1,0x36a73484,0x39503892,0x393d3854,0x3a9139fb,0x3abb3a0c,0x3b743b0f,0x3bad3b47,0x3bed3bbe,0x3c003beb,0x3bf63c00,0x3bae3beb,
0x3c003bf0,0x3be53ba0,0x3bc53bf2,0x3bef3c00,0x3b163b7c,0x3b4d3bb3,0x39fd3a96,0x3a0e3ac0,0x388b394e,0x384c393b,0x35a8376c,0x345a368a,0x2f97339c,0xa4203023,0xafe298b6,0xb4d8b128,
0x31c93531,0x355b37e0,0xaf652839,0x9d7f315a,0xb66db42f,0xb584b1b0,0xb939b844,0xb925b803,0xbac5ba10,0xbaecba20,0xbbb9bb53,0xbbdfbb82,0xbbffbbf2,0xbbe3bc00,0xbb91bbde,0xbaf7bb8a,
0xbbd6bb81,0xbb7cbadf,0xbbf5bbfd,0xbc00bbdd,0xbb5abbbe,0xbb88bbe3,0xba12baca,0xba22baf0,0xb83cb936,0xb7f6b923,0xb405b651,0xb15ab567,0x2a61ae84,0x31e22052,0x358a3269,0x381935a8,
0xb309b5e2,0xb5f4b841,0x2da3ac44,0xa5b2b269,0x363433b4,0x35493103,0x39343834,0x392137e6,0x3acf3a14,0x3af53a24,0x3bc43b60,0x3be73b8d,0x3bfb3bf8,0x3bd63bff,0x3b703bce,0x3ac63b6d,
0x3bc53b5f,0x3b5d3aad,0x3bfa3bf9,0x3bff3bcf,0x3b663bc9,0x3b923bea,0x3a163ad4,0x3a263afa,0x382c3931,0x37d5391e,0x335f3617,0x30ac352c,0xad582cc2,0xb2f0a89d,0xb63ab3a8,0xb869b63f,
0x34233690,0x368a3890,0xabc02e6b,0x2a613377,0xb5fab309,0xb50eb055,0xb92fb824,0xb91cb7c5,0xbad9ba18,0xbafeba28,0xbbcebb6c,0xbbedbb97,0xbbf6bbfc,0xbbc7bbfd,0xbb4cbbba,0xba93bb4d,
0xbbafbb38,0xbb3cba77,0xbbfebbf2,0xbbfcbbbf,0xbb72bbd3,0xbb9cbbf0,0xba1abadd,0xba2abb03,0xb81cb92d,0xb7b4b919,0xb2b3b5dc,0xaffbb4f0,0x2f7ea9fd,0x33fd2c12,0x36e53472,0x38b636d4,
0xb4c0b73a,0xb71eb8dc,0x2839b048,0xacf4b441,0x35bf325d,0x34d22f4c,0x392a3813,0x391737a4,0x3ae23a1c,0x3b073a2c,0x3bd73b77,0x3bf33ba1,0x3bee3bff,0x3bb63bfa,0x3b233ba4,0x3a5b3b2a,
0x3b973b0d,0x3b183a3e,0x3c003be9,0x3bf73bad,0x3b7d3bdb,0x3ba63bf5,0x3a1e3ae7,0x3a2e3b0c,0x380b3928,0x37933914,0x320735a2,0x2e9d34b4,0xb0d124e9,0xb484add5,0xb78eb50e,0xb901b767,
0xb97239ba,0x39dc3996,0xb8323ab5,0x3ad0385d,0x3927b9fe,0xba1fb94d,0x37b7bae9,0xbb02b807,0xb8d83a3f,0x3a5e3900,0xb7053b1a,0x3b30375e,0x3887ba7c,0xba99b8b0,0x364ebb46,0xbb5ab6aa,
0xb90039dc,0x3a3f3972,0xad7e3be6,0x3bf83115,0x3807ba99,0xbae9b887,0xabd9bc00,0xbbfca248,0xb5f13b30,0x3b6e3705,0x32a13bed,0x3bd4b04e,0x3365bba0,0xbbc9b4d5,0xb593bbaf,0xbb803475,
0xb88739fe,0x3a99394d,0x35f13bbc,0x3b6eb414,0x3593bb1a,0xbb80b75e,0xb8b0bb02,0xba7c37b7,0xaf0e3bc9,0x3bf43365,0x3a1f39dc,0x3927b972,0xb04ebc00,0xbbed2248,0xbb30b85d,0xb7053ab5,
0xb8073a1f,0x3ae93927,0x39fe3a3f,0x394db900,0x31dbbb80,0xbbddb593,0xbb6eb832,0xb5f13ad0,0x31153c00,0x3be62248,0x3bff32a1,0x28b6bbd4,0xb7b7bb91,0xbb023534,0xbba0304e,0x34d53bed,
0xb7053a3f,0x3b303900,0x3bbc375e,0x3414bb1a,0x2248bbc9,0xbc00b365,0xbbdda8b6,0x31db3bff,0x36aa3bd4,0x3b46b2a1,0x3a7cb64e,0xb8b0bb5a,0xba1fba5e,0xb92738d8,0xb7b739fe,0x3b02394d,
0xb5f13a5e,0x3b6e38d8,0x3bd42bd9,0xb2a1bbfc,0xb115bbf4,0xbbe6af0e,0xb9dc375e,0x39723b1a,0x39273b46,0x3a1fb6aa,0x3475bad0,0xbbafb832,0xbb91b887,0xb5343a99,0x34143c00,0x3bbc2248,
0xb4d53a7c,0x3ba038b0,0x3a3fb593,0xb900bb80,0xb534bc00,0xbb912248,0xb4143ab5,0x3bbc385d,0x3a993a5e,0x3887b8d8,0xb5f1bbfc,0xbb6e2bd9,0xbbffb475,0x28b63baf,0x3ad03a1f,0x3832b927,
0xb3653a99,0x3bc93887,0x36aab996,0xbb46b9ba,0xb7b7bbed,0xbb02304e,0x34d53bfc,0x3ba02bd9,0x3b913927,0x3534ba1f,0xbae9ba3f,0xb8073900,0xbb5a28b6,0x364e3bff,0x3bd43115,0xb2a1bbe6,
0xb1153ab5,0x3be6385d,0xa8b6bb6e,0xbbffb5f1,0xb900bbbc,0xba3f3414,0x3a1f3b30,0x3927b705,0x3bfc375e,0x2bd9bb1a,0xbbedb475,0x304e3baf,0xb9ba3593,0x39963b80,0x3887b832,0xba99bad0,
0xad7e3ad0,0x3bf83832,0xb7b7bbff,0xbb0228b6,0xb9febb6e,0xb94d35f1,0x3bed3887,0x304eba99,0x3bd43414,0xb2a1bbbc,0xb9963534,0x39ba3b91,0xb6aa3900,0x3b463a3f,0xb115bba0,0xbbe6b4d5,
0xa2483ae9,0x3c003807,0xba99bb30,0xb8873705,0xbad0bb02,0xb83237b7,0x3b462d7e,0xb6aabbf8,0x3b1a28b6,0xb75ebbff,0xaf0e3a7c,0x3bf438b0,0xabd93ab5,0x3bfc385d,0xba5ebb5a,0xb8d8364e,
0x2bd93b02,0x3bfc37b7,0xbbedb927,0xb04e3a1f,0xbb6eba7c,0xb5f138b0,0x385db6aa,0xbab5bb46,0x39dcb1db,0xb972bbdd,0x38323c00,0x3ad02248,0x34d53bbc,0x3ba03414,0xbbf4b705,0x2f0e3b30,
0x304e3b1a,0x3bed375e,0xbb91b475,0x35343baf,0xbbd4b9dc,0xb2a13972,0x2248ba7c,0xbc00b8b0,0x3832b64e,0xbad0bb5a,0x3b803a99,0x3593b887,0x39003bfc,0x3a3fabd9,0xb9273414,0x3a1f3bbc,
0x32a13b30,0x3bd43705,0xb996304e,0x39ba3bed,0xbbffb927,0xa8b63a1f,0xb832bbf4,0xbad0af0e,0x3475b8b0,0xbbafba7c,0x3ba03593,0xb4d5bb80,0x3ae93b6e,0x3807b5f1,0x2bd93a99,0x3bfc3887,
0x34753b46,0x3baf36aa,0xb4d53832,0x3ba03ad0,0xbbedb85d,0x304e3ab5,0xbb30bb5a,0xb705364e,0x2248b9fe,0xbc00b94d,0x3887b414,0xba99bbbc,0x3be63a1f,0x3115b927,0x39dc3bf4,0x3972af0e,
0x35933b5a,0x3b80364e,0x31153a99,0x3be63887,0xbba0b705,0x34d53b30,0xbbf4b8d8,0x2f0e3a5e,0xb414bb02,0xbbbcb7b7,0xabd9ba1f,0xbbfcb927,0x3bd43832,0xb2a1bad0,0x3c003972,0xa248b9dc,
0x36aa3b6e,0x3b4635f1,0x38b03bdd,0x3a7c31db,0xbb1ab534,0x375e3b91,0xba3fb04e,0x39003bed,0xb807bbaf,0xbae9b475,0xb94dbbf8,0xb9fead7e,0x3ab53365,0xb85dbbc9,0x39ba28b6,0xb996bbff,
0x37b73b80,0x3b023593,0x3b1a3bc9,0x375eb365,0xba5eb2a1,0x38d83bd4,0xb53435f1,0x3b913b6e,0xb9babbfc,0xb996abd9,0xbbddbae9,0xb1db3807,0x38b0ad7e,0xba7cbbf8,0x28b6b900,0xbbffba3f,
0x385d3b91,0x3ab53534,0x3c003a5e,0x2248b8d8,0xb972ad7e,0x39dc3bf8,0x33653a3f,0x3bc93900,0xbb02bbe6,0xb7b73115,0xbb1ab6aa,0x375e3b46,0x3414b64e,0xbbbcbb5a,0xb94dbbdd,0xb9feb1db,
0x38d83ba0,0x3a5e34d5,0x3b3037b7,0xb705bb02,0xb85d28b6,0x3ab53bff,0x39ba3be6,0x39963115,0xbbc9bb6e,0xb36535f1,0xb6aa31db,0x3b463bdd,0xaf0eb94d,0xbbf4b9fe,0xbbf8bae9,0xad7e3807,
0x394d3baf,0x39fe3475,0x38d82d7e,0xba5ebbf8,0xb64e3115,0x3b5a3be6,0x3bd43b80,0x32a1b593,0xbbffba99,0x28b63887,0x336539ba,0x3bc93996,0xb75ebae9,0xbb1ab807,0xba3fb534,0x39003b91,
0x39ba3bbc,0x39963414,0x31dbb534,0xbbddbb91,0xb3653475,0x3bc93baf,0x3b803927,0xb593ba1f,0xbba0b972,0x34d539dc,0x3a3f3be6,0x39003115,0xb9febbd4,0xb94db2a1,0xb04e35f1,0x3bed3b6e,
0x3a1f3bc9,0x39273365,0xb475b972,0xbbafb9dc,0xabd9364e,0x3bfc3b5a,0x38d831db,0xba5ebbdd,0xbab5b807,0x385d3ae9,0x3c003b30,0x2248b705,0xbb80bbf4,0xb5932f0e,0x38b03b1a,0x3a7c375e,
0x3a7c3bd4,0x38b032a1,0xb972bb5a,0xb9dcb64e,0x2f0e3807,0x3bf43ae9,0x2d7eb534,0xbbf8bb91,0xb94db4d5,0x39fe3ba0,0x3a5e37b7,0xb8d8bb02,0xbc00bb46,0x224836aa,0x3bdd3bc9,0x31dbb365,
0x3ad03bdd,0x383231db,0xbb80bc00,0xb5932248,0x347538d8,0x3baf3a5e,0xb75eb9fe,0xbb1ab94d,0xb705ad7e,0x3b303bf8,0x3414af0e,0xbbbcbbf4,0xbb6eb9dc,0x35f13972,0x3ab538b0,0xb85dba7c,
0x3b1a3be6,0x375e3115,0xbbf4bb46,0x2f0e36aa,0x37053996,0x3b3039ba,0xbae9bbd4,0xb807b2a1,0xb1db304e,0x3bdd3bed,0xb64eb94d,0xbb5ab9fe,0xb9dcb7b7,0x39723b02,0x3365ad7e,0xbbc9bbf8,
0x3b5a3bed,0x364e304e,0xbab5b94d,0x385d39fe,0x38b03a3f,0x3a7c3900,0xbbffbba0,0x28b634d5,0x2d7e3593,0x3bf83b80,0xbb02bbc9,0xb7b7b365,0xb705b1db,0x3b303bdd,0xb807b9ba,0xbae9b996,
0x3b913bf4,0x35342f0e,0xb807b4d5,0x3ae93ba0,0x39ba3ad0,0x39963832,0xba99b972,0x388739dc,0x3593385d,0x3b803ab5,0xbbe6bb6e,0x311535f1,0xad7e304e,0x3bf83bed,0xbbafbbfc,0xb475abd9,
0x3bbc3bf8,0x34142d7e,0xabd92f0e,0x3bfc3bf4,0x3a993b46,0x388736aa,0xb64eb365,0x3b5a3bc9,0x38b039ba,0x3a7c3996,0xb972b85d,0x39dc3ab5,0x34753705,0x3baf3b30,0xbb1aba5e,0x375e38d8,
0x3bdd3bfc,0x31db2bd9,0x364e3807,0x3b5a3ae9,0x3b463ba0,0x36aa34d5,0x31153475,0x3be63baf,0x3a3f3ad0,0x39003832,0xad7e28b6,0x3bf83bff,0x38d83996,0x3a5e39ba,0xb534b2a1,0x3b913bd4,
0x3bf43bff,0x2f0e28b6,0x3a1f3a7c,0x392738b0,0x3bbc3bdd,0x341431db,0x394d39ba,0x39fe3996,0x3b5a3b91,0x364e3534,0x385d38d8,0x3ab53a5e,0x3ad03b1a,0x3832375e,0x36aa37b7,0x3b463b02,
0x3bff3c00,0x28b62248,0x3bc93bd4,0x336532a1,0x3bf83bfc,0x2d7e2bd9,0x3baf3bbc,0x34753414,0x3bed3bf4,0x304e2f0e,0x3b913ba0,0x353434d5,0x3bdd3be6,0x31db3115,0x3b6e3b80,0x35f13593,
0xb5933b6e,0x3b8035f1,0xb1153bdd,0x3be631db,0x34d5bb91,0xbba0b534,0x2f0ebbed,0xbbf4b04e,0xb4143baf,0x3bbc3475,0xabd93bf8,0x3bfc2d7e,0x32a1bbc9,0xbbd4b365,0x2248bbff,0xbc00a8b6,
0x37b73b46,0x3b02b6aa,0x3b1a3832,0x375ebad0,0xb8d8bab5,0xba5e385d,0xbb91b64e,0xb5343b5a,0x39ba39fe,0x3996b94d,0x3bdd3414,0x31dbbbbc,0xba7cb927,0xb8b03a1f,0xbbffaf0e,0xa8b63bf4,
0x3bd43534,0x32a1bb91,0x39bab8d8,0xb996ba5e,0xbbffad7e,0x28b63bf8,0xb8323a3f,0x3ad03900,0x3bafb115,0xb475bbe6,0x34d5bb46,0xbba0b6aa,0xbae9364e,0x38073b5a,0xabd93bdd,0x3bfc31db,
0x3a5eb75e,0xb8d8bb1a,0xb705bbaf,0xbb303475,0xb85d39dc,0x3ab53972,0x39ba3a7c,0x3996b8b0,0x3365bb5a,0xbbc9b64e,0xbb46b887,0xb6aa3a99,0x2f0e3bfc,0x3bf42bd9,0x3bf83414,0x2d7ebbbc,
0x2bd9bbaf,0xbbfcb475,0xbbedad7e,0x304e3bf8,0x35f13be6,0x3b6eb115,0x3ab5b593,0xb85dbb80,0xb9dcba99,0xb9723887,0xb83239ba,0x3ad03996,0x3ba03807,0x34d5bae9,0x2f0ebb91,0xbbf4b534,
0xb9babae9,0xb9963807,0xb1db3b30,0x3bdd3705,0x3bc937b7,0x3365bb02,0xb593bbf8,0xbb802d7e,0xbba028b6,0x34d53bff,0x3a3f3a7c,0x3900b8b0,0x394db85d,0xb9febab5,0xbbedb64e,0xb04e3b5a,
0xbbf8b365,0x2d7e3bc9,0x3b0239dc,0x37b7b972,0x39feb64e,0xb94dbb5a,0xbbedb1db,0x304e3bdd,0xb2a13ae9,0x3bd43807,0x39bab705,0xb996bb30,0xb6aabbf4,0xbb462f0e,0xb1153b1a,0x3be6375e,
0xb8b0385d,0x3a7c3ab5,0x39dcb5f1,0xb972bb6e,0xaf0ebbbc,0xbbf4b414,0xad7e3b30,0x3bf83705,0x39fe3b1a,0x394db75e,0xb8d8bbaf,0xba5e3475,0xbc00b593,0x22483b80,0x3bdd3832,0x31dbbad0,
0x33653bdd,0x3bc931db,0xb6aabc00,0xbb462248,0xbb02ba5e,0xb7b738d8,0x3ba0394d,0x34d5b9fe,0x3b912d7e,0xb534bbf8,0xbae92f0e,0x38073bf4,0xb64e3972,0x3b5a39dc,0x32a1ba7c,0xbbd4b8b0,
0x3b1a3a7c,0x375eb8b0,0xbbf4b593,0x2f0e3b80,0xbb30a248,0x37053c00,0x3807b85d,0xbae9bab5,0x31dbba5e,0xbbddb8d8,0x364e3bfc,0x3b5a2bd9,0x39723baf,0x39dcb475,0xbbc9b927,0xb3653a1f,
0x3b6e304e,0xb5f1bbed,0xb2a139fe,0x3bd4394d,0xb1153a3f,0x3be63900,0xb9dcbba0,0xb97234d5,0xba1fbb80,0xb9273593,0x3baf3365,0xb475bbc9,0x3b9131db,0xb534bbdd,0xb41439ba,0x3bbc3996,
0x3534b900,0xbb91ba3f,0x3ae93b1a,0x3807b75e,0x39ba3bc9,0x3996b365,0xba9928b6,0x38873bff,0xbb80b2a1,0x35933bd4,0xb115bb5a,0xbbe6b64e,0x2d7eba5e,0xbbf8b8d8,0x3baf39fe,0x3475b94d,
0xb807bbf8,0xbae9ad7e,0x39feaf0e,0xb94dbbf4,0x3bdd36aa,0xb1dbbb46,0x35f13bc9,0x3b6e3365,0xb11539ba,0x3be63996,0xbbffb85d,0x28b63ab5,0xbb02bb30,0xb7b73705,0x34d5b8d8,0xbba0ba5e,
0xbbddb9fe,0xb1db394d,0xb64ebbbc,0xbb5ab414,0x36aab75e,0xbb46bb1a,0x3be637b7,0xb115bb02,0x3a3f3bc9,0x3900b365,0xad7e39dc,0x3bf83972,0xba5ea248,0x38d83c00,0xbb91bab5,0xb534385d,
0xba3fa8b6,0x39003bff,0xbbf8b8b0,0x2d7e3a7c,0xb807bbdd,0xbae9b1db,0x2bd9b9ba,0xbbfcb996,0x3b6e3534,0xb5f1bb91,0x3bd43a5e,0x32a1b8d8,0x33653b1a,0x3bc9375e,0xb59337b7,0x3b803b02,
0xa8b63996,0x3bff39ba,0xb365385d,0x3bc93ab5,0xbbf8b9fe,0xad7e394d,0xbbafbae9,0xb4753807,0x304eb900,0xbbedba3f,0x3534b75e,0xbb91bb1a,0x3bdd3a7c,0x31dbb8b0,0x3b6e3b46,0x35f1b6aa,
0x39dc3c00,0x3972a248,0x3ad03bd4,0x3832b2a1,0xb9272bd9,0x3a1f3bfc,0xb7b73414,0x3b023bbc,0xba5ebbf4,0xb8d82f0e,0xbb30bba0,0xb70534d5,0x3887b115,0xba99bbe6,0x364eb593,0xbb5abb80,
0x3bf43972,0xaf0eb9dc,0x3a1f3115,0xb927bbe6,0x34143a99,0x3bbc3887,0x39fe3c00,0x394d2248,0xbb5ab705,0x364e3b30,0xb85d304e,0x3ab53bed,0xb832bba0,0xbad0b4d5,0xbb46bbaf,0xb6aa3475,
0x3887abd9,0xba99bbfc,0xb5f1bae9,0xbb6eb807,0x3b803ba0,0x3593b4d5,0x3a7c3475,0xb8b0bbaf,0xaf0e3832,0x3bf43ad0,0x3a1f3bff,0x392728b6,0xbbedb996,0x304e39ba,0xb70532a1,0x3b303bd4,
0xb414ba1f,0xbbbcb927,0xbbfcba3f,0x2bd93900,0x3a993593,0xb887bb80,0xb64ebad0,0xbb5ab832,0x3a7c3c00,0x38b02248,0x39dc32a1,0xb972bbd4,0xb4753534,0x3baf3b91,0x3b1a3bed,0x375eb04e,
0xbb30bbf4,0xb7052f0e,0xb41434d5,0x3bbc3ba0,0x2248b832,0xbc00bad0,0xbbddb9dc,0x31db3972,0x3b46385d,0xb6aabab5,0xb8b0bb6e,0xba7cb5f1,0x3a1f3bed,0x3927304e,0x37b7abd9,0xbb02bbfc,
0xbb5ab8d8,0x364e3a5e,0x3ab53bfc,0x385d2bd9,0xba7cbbf4,0xb8b0af0e,0xa8b6375e,0x3bff3b1a,0x2d7eb6aa,0xbbf8bb46,0xbb02b832,0x37b73ad0,0x3b303887,0xb705ba99,0xbae9bc00,0xb807a248,
0xb4d53115,0x3ba03be6,0x3a3f36aa,0xb900bb46,0xbb91b996,0x353439ba,0x3bbc3bd4,0x3414b2a1,0xba99bbed,0xb887b04e,0x35f139fe,0x3b6e394d,0xa8b6b7b7,0xbbffbb02,0xb832ad7e,0x3ad03bf8,
0x38323a99,0x3ad03887,0xb593b996,0xbb80b9ba,0xb475304e,0x3baf3bed,0x375e2bd9,0xbb1abbfc,0xbb30b927,0x37053a1f,0x3bbc3a3f,0xb414b900,0xbb6ebbff,0xb5f128b6,0x3ab53be6,0x385d3115,
0x3be63bd4,0x3115b2a1,0xbbffbb5a,0x28b6364e,0x39003ae9,0x3a3f3807,0xba1fbb91,0xb927b534,0xabd934d5,0x3bfc3ba0,0xb04eb7b7,0xbbedbb02,0xb9bab6aa,0x39963b46,0x38873365,0xba99bbc9,
0x3a1f3832,0xb927bad0,0xb47528b6,0x3baf3bff,0x3bfc3b6e,0xabd9b5f1,0xba5eb887,0x38d83a99,0x3ab53bbc,0x385d3414,0xbc00bb91,0x22483534,0x35933900,0x3b803a3f,0xba7cbba0,0xb8b0b4d5,
0x2248b414,0xbc00bbbc,0x3a993b91,0x38873534,0x38323475,0xbad0bbaf,0x36aa3927,0x3b463a1f,0x3b1a39dc,0xb75eb972,0xaf0e3115,0x3bf43be6,0x3bfc3bd4,0x2bd9b2a1,0xb8d8b5f1,0x3a5e3b6e,
0xb9febb02,0xb94db7b7,0x3a5e3927,0xb8d8ba1f,0xb64eb8b0,0xbb5aba7c,0x3bd43b46,0xb2a1b6aa,0x28b6b1db,0xbbffbbdd,0x3bc93c00,0x33652248,0x375e3414,0xbb1abbbc,0x3a3f3b30,0x39003705,
0xbbedbba0,0x304e34d5,0xb534b7b7,0xbb91bb02,0xbbd4bbff,0xb2a1a8b6,0x2248b115,0xbc00bbe6,0xbad0bb6e,0xb832b5f1,0x359331db,0xbb80bbdd,0xb900b9fe,0xba3fb94d,0x39273807,0xba1fbae9,
0xb85db705,0x3ab53b30,0xbc00bbed,0x2248304e,0xb9dcb927,0x39723a1f,0xbbc9bbf4,0xb365af0e,0xbb02ba7c,0x37b738b0,0xbb1abb80,0xb75eb593,0xbbbcbb6e,0x341435f1,0xb9feba99,0xb94db887,
0x34753593,0x3baf3b80,0xb4d5b365,0x3ba03bc9,0x304e32a1,0x3bed3bd4,0xb705b5f1,0x3b303b6e,0xa2482bd9,0x3c003bfc,0xb887b807,0x3a993ae9,0xb115ad7e,0x3be63bf8,0xb972b900,0x39dc3a3f,
0x3b463b5a,0x36aa364e,0x3a7c3a99,0x38b03887,0x3b1a3b30,0x375e3705,0x3a3f3a5e,0x390038d8,0x3ae93b02,0x380737b7,0x39fe3a1f,0x394d3927,0x3ab53ad0,0x385d3832,0x39ba39dc,0x39963972,
0x28b63c00,0x3bffa248,0x33653bd4,0x3bc9b2a1,0xad7ebbfc,0xbbf82bd9,0xb475bbbc,0xbbaf3414,0x304e3bf4,0x3bedaf0e,0x35343ba0,0x3b91b4d5,0xb1dbbbe6,0xbbdd3115,0xb5f1bb80,0xbb6e3593,
0x3bf4a8b6,0xaf0ebbff,0x3a1fb8b0,0xb927ba7c,0xbbbc31db,0x34143bdd,0xb94d3996,0x39fe39ba,0x3b5ab534,0xb64ebb91,0x385dba5e,0xbab5b8d8,0xbad0375e,0x38323b1a,0xb6aa3b02,0x3b4637b7,
0xb1dbbbfc,0xbbdd2bd9,0xbb5ab807,0xb64e3ae9,0x36aa3ba0,0x3b46b4d5,0x3be63475,0x3115bbaf,0xb900bad0,0xba3f3832,0xbbf8a8b6,0x2d7e3bff,0x3a5e3996,0x38d8b9ba,0x3b91b2a1,0xb534bbd4,
0xbbbc2d7e,0x34143bf8,0x2bd93bf4,0x3bfc2f0e,0x3a99b6aa,0xb887bb46,0xb64ebbc9,0xbb5a3365,0xb8b03996,0x3a7c39ba,0x39723ab5,0x39dcb85d,0x3475bb30,0xbbafb705,0xbb1ab8d8,0xb75e3a5e,
0x35343bf4,0x3b91af0e,0x3ae9b4d5,0xb807bba0,0xb996bad0,0xb9ba3832,0xb8873972,0x3a9939dc,0x3b80385d,0x3593bab5,0x3115bb6e,0xbbe6b5f1,0xbbf8b04e,0x2d7e3bed,0x34753bfc,0x3bafabd9,
0x3b5ab04e,0xb64ebbed,0xbab5b9fe,0xb85d394d,0xb8b03900,0x3a7c3a3f,0x3bff34d5,0x28b6bba0,0x2d7ebb80,0xbbf8b593,0xbb023365,0x37b73bc9,0x37053bdd,0x3b30b1db,0x3807b996,0xbae9b9ba,
0xb75ebbe6,0xbb1a3115,0xaf0e3b46,0x3bf436aa,0x3b303996,0x3705b9ba,0xb807bbd4,0xbae932a1,0xbbddb04e,0x31db3bed,0x3b5a394d,0x364eb9fe,0x3972b7b7,0xb9dcbb02,0xbbc9ad7e,0x33653bf8,
0xbad031db,0x38323bdd,0x3b802248,0xb593bc00,0x3475ba5e,0xbbafb8d8,0xb75e394d,0x3b1a39fe,0x37053bf8,0x3b30ad7e,0xb414bbf4,0xbbbcaf0e,0xbb6eb972,0xb5f139dc,0x3ab53a7c,0x385db8b0,
0x38b03bd4,0x3a7cb2a1,0xb9dcbb5a,0xb972364e,0xbbf4b807,0xaf0e3ae9,0x3bf83534,0xad7ebb91,0x39feb4d5,0xb94dbba0,0xb8d837b7,0x3a5e3b02,0xa2483b46,0x3c0036aa,0xb1dbbbc9,0xbbddb365,
0x3a1fb365,0xb927bbc9,0xb47539dc,0x3baf3972,0x2bd93b5a,0x3bfc364e,0xb8d8bbdd,0xba5e31db,0xbab5bae9,0xb85d3807,0x3c003705,0xa248bb30,0x3b802f0e,0xb593bbf4,0xb8b0375e,0x3a7c3b1a,
0xb996bbbc,0xb9ba3414,0x3bdd3534,0xb1dbbb91,0x3bc93475,0xb365bbaf,0xb5933927,0x3b803a1f,0xb4d53972,0x3ba039dc,0xb900bbe6,0xba3f3115,0xb94dbbd4,0xb9fe32a1,0x3bed35f1,0xb04ebb6e,
0xb94d3475,0x39fe3baf,0xb8d8bbf8,0xba5e2d7e,0xb64ebbe6,0xbb5ab115,0x3bd43593,0xb2a1bb80,0x3bff3887,0x28b6ba99,0xb3653996,0x3bc939ba,0xb75e3807,0x3b1a3ae9,0xba3fbb91,0xb9003534,
0x3a5e3ba0,0x38d8b4d5,0xb70537b7,0x3b303b02,0xbab5a8b6,0x385d3bff,0xb996bbe6,0xb9ba3115,0xb365bb6e,0xbbc9b5f1,0x3b4631db,0xb6aabbdd,0x3bf4394d,0x2f0eb9fe,0x2d7e3ae9,0x3bf83807,
0x385db534,0xbab5bb91,0x3c0038d8,0xa248ba5e,0x39723bf8,0x39dcad7e,0xb3653900,0x3bc93a3f,0xbb02b115,0x37b73be6,0xbb1abb46,0xb75e36aa,0xb414bb5a,0xbbbcb64e,0x394db1db,0xb9febbdd,
0xbb02bb80,0xb7b73593,0xb75ebbc9,0xbb1ab365,0x38d8b2a1,0xba5ebbd4,0x3b9135f1,0xb534bb6e,0x39963bfc,0x39baabd9,0x31db3ae9,0x3bdd3807,0xba7cad7e,0x38b03bf8,0xbbffb900,0x28b63a3f,
0xb6aa35f1,0x3b463b6e,0xb8b031db,0x3a7c3bdd,0xbb1abb91,0xb75e3534,0xba3fbbed,0xb900304e,0x3807b475,0xbae9bbaf,0x394dad7e,0xb9febbf8,0x3ab53bc9,0x385db365,0x39ba3bff,0x3996a8b6,
0x3b803b5a,0x3593b64e,0x3be63a99,0x3115b887,0xb4d53705,0x3ba03b30,0xaf0e38d8,0x3bf43a5e,0xbbbcbb02,0xb41437b7,0xbbfcba1f,0xabd93927,0x32a1b832,0xbbd4bad0,0x2248b972,0xbc00b9dc,
0x3475b6aa,0xbbafbb46,0xb4d5bad0,0xbba0b832,0x3bed3ab5,0x304eb85d,0x3b30364e,0xb705bb5a,0x2248394d,0x3c0039fe,0x38873bbc,0x3a993414,0xbbe6b927,0x31153a1f,0xb9dcaf0e,0x39723bf4,
0xbbd4bb30,0xb2a13705,0xb9bab04e,0x39963bed,0xa8b6b927,0xbbffba1f,0xbad0bbf4,0xb8322f0e,0x3baf38b0,0xb475ba7c,0x34d5b593,0xbba0bb80,0x38073b6e,0x3ae935f1,0x3bfc3a99,0x2bd9b887,
0xb04e375e,0x3bed3b1a,0x3b913baf,0x3534b475,0xbbd4b972,0x32a139dc,0x224838b0,0x3c003a7c,0xb832bb5a,0xbad0b64e,0xbb80b887,0x35933a99,0x39002bd9,0xba3fbbfc,0xb927bbbc,0xba1fb414,
0x3bfc3b02,0x2bd9b7b7,0xb04eb927,0xbbedba1f,0x35f13a7c,0x3b6e38b0,0x3ab536aa,0xb85dbb46,0xb972b1db,0x39dc3bdd,0x3ad03c00,0x3832a248,0xbba0bbbc,0xb4d53414,0xaf0e3705,0x3bf43b30,
0xa248b807,0xbc00bae9,0xba99b705,0x38873b30,0x3ad037b7,0xb832bb02,0xbb46bbf8,0xb6aa2d7e,0x3b1a3bff,0x375ea8b6,0xaf0eb8b0,0xbbf4ba7c,0x2bd9385d,0x3bfc3ab5,0x3a5e364e,0xb8d8bb5a,
0xbbf8bad0,0x2d7e3832,0x3b023bff,0x37b728b6,0xb94dbb6e,0xb9feb5f1,0x304e3887,0x3bed3a99,0x32a1b414,0xbbd4bbbc,0xb9bab534,0x39963b91,0x3b463900,0xb6aaba3f,0xbbe6bba0,0xb11534d5,
0x3115385d,0x3be63ab5,0x28b6b5f1,0xbbffbb6e,0xb900b414,0x3a3f3bbc,0x3a1f3705,0xb927bb30,0xbbfcbb1a,0x2bd9375e,0x3bed3baf,0x304eb475,0xb9babb80,0xb996b593,0x38873ad0,0x3a993832,
0x3bc93a99,0xb365b887,0xbb46b996,0x36aa39ba,0x3b023bed,0x37b7304e,0xbba0bbfc,0xb4d52bd9,0x35343927,0x3b913a1f,0xb807ba3f,0xbae9b900,0xb64ea8b6,0x3b5a3bff,0x32a1b115,0xbbd4bbe6,
0xb4d5b8b0,0xbba0ba7c,0x3a3f3b80,0x39003593,0x35342248,0xbb91bc00,0x3414385d,0x3bbc3ab5,0x3a9938d8,0xb887ba5e,0xb5f1abd9,0x3b6e3bfc,0x3bff3baf,0x28b6b475,0xbad0b927,0x38323a1f,
0xbb6eba5e,0x35f138d8,0x32a1abd9,0xbbd4bbfc,0xbbe6bbf4,0xb1152f0e,0x3972375e,0xb9dcbb1a,0xba1fbb46,0xb927b6aa,0x3baf3ad0,0xb475b832,0xb534b887,0xbb91ba99,0x3bbc3c00,0x3414a248,
0x37053900,0x3b303a3f,0xbbbcbb1a,0x3414375e,0x22483365,0x3c003bc9,0xbbddbbff,0xb1db28b6,0xb6aab2a1,0x3b463bd4,0xba7cbb5a,0xb8b0b64e,0xba1fb8d8,0x39273a5e,0xb7b7b94d,0xbb02b9fe,
0x3ae93a1f,0xb807b927,0x394d3a3f,0x39fe3900,0x3bdd3b80,0xb1dbb593,0x35f13832,0x3b6e3ad0,0x3be63c00,0x3115a248,0x28b632a1,0x3bff3bd4,0x3b023b91,0x37b73534,0xb4d5b04e,0x3ba03bed,
0xb887b94d,0xba99b9fe,0x35f13414,0xbb6ebbbc,0xb593b75e,0xbb80bb1a,0x38b037b7,0xba7cbb02,0xaf0eb365,0xbbf4bbc9,0x3a1f3972,0xb927b9dc,0x304e2248,0xbbedbc00,0x3b303ab5,0xb705b85d,
0xba3fb9dc,0x39003972,0xbbf8bbe6,0x2d7e3115,0xbae9ba99,0x38073887,0xbbfcbc00,0xabd92248,0xbb6ebb30,0x35f13705,0xbbd4bbed,0xb2a1b04e,0xbbc9bba0,0x336534d5,0xbb80bbaf,0xb593b475,
0x39723996,0x39dc39ba,0x3832385d,0x3ad03ab5,0x3927394d,0x3a1f39fe,0x37b73807,0x3b023ae9,0x38d83900,0x3a5e3a3f,0x3705375e,0x3b303b1a,0x388738b0,0x3a993a7c,0x364e36aa,0x3b5a3b46,
0x36aa3b5a,0x3b46b64e,0x38b03a99,0x3a7cb887,0xb75ebb30,0xbb1a3705,0xb900ba5e,0xba3f38d8,0x38073b02,0x3ae9b7b7,0x394d3a1f,0x39feb927,0xb85dbad0,0xbab53832,0xb996b9dc,0xb9ba3972,
0x3475bb80,0xbbafb593,0xb4d5bbc9,0xbba03365,0xb04e3bd4,0x3bed32a1,0x37053b6e,0x3b30b5f1,0xa248bbfc,0xbc00abd9,0xb887bae9,0xba993807,0x31153bf8,0x3be6ad7e,0x39723a3f,0x39dcb900,
0xbab53705,0x385d3b30,0xa2483bed,0x3c00304e,0x3972b927,0xb9dcba1f,0xb365bbf4,0xbbc92f0e,0xb7b73a7c,0x3b0238b0,0x375e3b80,0x3b1ab593,0x3414bb6e,0xbbbcb5f1,0xb94dba99,0xb9fe3887,
0x3bed34d5,0x304ebba0,0x3534bb02,0xbb91b7b7,0xbbd428b6,0x32a13bff,0x22483be6,0x3c003115,0x3ad0b5f1,0xb832bb6e,0xb593bbdd,0xbb8031db,0xb900394d,0x3a3f39fe,0x39273ae9,0x3a1fb807,
0xb94dbb02,0xb9fe37b7,0xb8d83927,0x3a5e3a1f,0x3b5a38b0,0x364eba7c,0x32a1bb46,0xbbd4b6aa,0xbbffb1db,0x28b63bdd,0x33653c00,0x3bc9a248,0x3b1ab414,0xb75ebbbc,0xb900bb30,0xba3f3705,
0x22483bbc,0x3c003414,0x3a99b534,0xb887bb91,0xb832bbaf,0xbad03475,0xb6aa3a1f,0x3b463927,0x3b1a3972,0x375eb9dc,0xaf0ebbe6,0xbbf4b115,0xbbfcb2a1,0x2bd93bd4,0x38d83b6e,0x3a5eb5f1,
0x3927b832,0xba1fbad0,0xbbafa8b6,0x34753bff,0xabd93b6e,0x3bfc35f1,0x38d8b887,0xba5eba99,0xb85dbbbc,0xbab53414,0xa2483b91,0x3c003534,0x3b803900,0x3593ba3f,0xb8b0bba0,0xba7c34d5,
0xbbe6b2a1,0x31153bd4,0x3bff364e,0x28b6bb5a,0x3900b807,0xba3fbae9,0xba1f3534,0x39273b91,0x2bd93ba0,0x3bfc34d5,0x304ebb02,0xbbedb7b7,0xb9babb46,0xb99636aa,0x38873bc9,0x3a99b365,
0x3ad03a99,0x3832b887,0xbb80b996,0xb59339ba,0xbbafb04e,0x34753bed,0x3b1aabd9,0xb75ebbfc,0x3705b927,0xbb30ba1f,0xb4143a3f,0x3bbc3900,0x35f13bff,0x3b6e28b6,0xb85dbbe6,0xbab53115,
0xb4d5bbe6,0xbba0b115,0x3a3f3b46,0x3900b6aa,0x3b9139ba,0x3534b996,0xbbbcb2a1,0x34143bd4,0xba99304e,0x38873bed,0x35f1b94d,0xbb6eb9fe,0x28b6bb02,0xbbffb7b7,0x38323bf8,0x3ad0ad7e,
0xb64e38d8,0x3b5a3a5e,0xb85dbbfc,0xbab52bd9,0xb8b0bbf4,0xba7c2f0e,0x3bff375e,0xa8b6bb1a,0x3bf836aa,0xad7ebb46,0xb7b73832,0x3b023ad0,0xb7053887,0x3b303a99,0xb807bc00,0xbae92248,
0x3b302f0e,0xb705bbf4,0x34143ba0,0x3bbc34d5,0x22483ad0,0x3c003832,0xbbddb972,0xb1db39dc,0xbb46bab5,0xb6aa385d,0x38b0b5f1,0xba7cbb6e,0x3a1fb04e,0xb927bbed,0x37b73bfc,0x3b022bd9,
0xbbbcba1f,0xb4143927,0x2bd9ba3f,0xbbfcb900,0x3887b593,0xba99bb80,0x3b5a3ad0,0x364eb832,0x38b03c00,0x3a7ca248,0xb97232a1,0x39dc3bd4,0xbbafb534,0x34753b91,0xb75ebbed,0xbb1ab04e,
0x38873bfc,0x3a992bd9,0xb5f13807,0x3b6e3ae9,0xbb80b4d5,0x35933ba0,0xba7cbbaf,0xb8b03475,0xaf0ebad0,0xbbf4b832,0x3a1fa8b6,0xb927bbff,0x3bed39ba,0x304eb996,0x37053bd4,0x3b3032a1,
0x2f0eb972,0xbbf4b9dc,0x3927b115,0xba1fbbe6,0x3bbc3a99,0x3414b887,0x394d3c00,0x39fea248,0xb64e3705,0x3b5a3b30,0xbab5b04e,0x385d3bed,0xbad0bba0,0xb83234d5,0xb6aabbaf,0xbb46b475,
0xb9dca248,0x39723c00,0xbad0b2a1,0x38323bd4,0xb927bbfc,0xba1fabd9,0xb7b7bbbc,0xbb02b414,0x3a5e2f0e,0xb8d8bbf4,0x3b3034d5,0xb705bba0,0x38873be6,0x3a993115,0x364e3b80,0x3b5a3593,
0x3bff3996,0xa8b6b9ba,0x3bc9385d,0xb365bab5,0x2d7e39fe,0x3bf8394d,0x34753ae9,0x3baf3807,0xbbedb900,0x304e3a3f,0xbb91b75e,0x35343b1a,0xb1dbba7c,0xbbddb8b0,0xb5f1bb46,0xbb6eb6aa,
0xba3fbbff,0xb90028b6,0xbbf8ba7c,0xad7e38b0,0x3807b1db,0xbae9bbdd,0xabd9b996,0xbbfcb9ba,0x3b6e3b91,0x35f1b534,0x3bd438d8,0xb2a1ba5e,0xb365375e,0x3bc93b1a,0x35933b02,0x3b8037b7,
0x31db39fe,0x3bdd394d,0x3b5a3bbc,0x364eb414,0xbb46b75e,0x36aa3b1a,0xb11537b7,0x3be63b02,0xb900bbc9,0xba3fb365,0xbbf8b9dc,0x2d7e3972,0x38d8a248,0xba5ebc00,0xb534bab5,0xbb91b85d,
0x3807ad7e,0xbae9bbf8,0xb9febbf4,0xb94daf0e,0x3bdd3b46,0x31dbb6aa,0x35f1b365,0xbb6ebbc9,0x31153996,0x3be639ba,0x3bff3ab5,0x28b6b85d,0xbb02b705,0x37b73b30,0x34d53a5e,0x3ba038d8,
0xbb91b900,0x35343a3f,0x38073b1a,0x3ae9375e,0xb996bbc9,0xb9bab365,0xb887a8b6,0x3a993bff,0x3593b2a1,0xbb80bbd4,0xbbe6bb5a,0xb115364e,0x3bf83a5e,0xad7eb8d8,0xb475b9fe,0xbbafb94d,
0x3b6e3bed,0x35f1b04e,0xb2a1b94d,0xbbd4b9fe,0x31153900,0x3be63a3f,0x39dc34d5,0xb972bba0,0xba1fb593,0x39273b80,0x3baf3bc9,0x3475b365,0xbb91bbdd,0xb53431db,0x34143996,0x3bbc39ba,
0xb75eba7c,0xbb1ab8b0,0xaf0e3593,0x3bf43b80,0x3705a248,0xbb30bc00,0xbae9b85d,0x38073ab5,0x3bdd3a5e,0xb1dbb8d8,0xbb5abbfc,0xb64e2bd9,0x39dc3baf,0x39723475,0xb365b927,0xbbc9ba1f,
0xb36531db,0x3bc93bdd,0x36aa2248,0xbb46bc00,0xbb02b8d8,0x37b73a5e,0x3ba039fe,0xb4d5b94d,0xbb91bbf8,0xb5342d7e,0x3ae93bf4,0x38072f0e,0xb64eb9dc,0xbb5ab972,0x32a138b0,0x3bd43a7c,
0x3a7c385d,0xb8b0bab5,0xb972b5f1,0x39dc3b6e,0x3bf43bbc,0x2f0eb414,0xbbf8bb30,0x2d7e3705,0x394d3b1a,0x39fe375e,0xba5ebbaf,0xb8d8b475,0xa2483593,0x3c003b80,0xb1dbb832,0xbbddbad0,
0xbbf8bbc9,0xad7e3365,0x3b023972,0xb7b7b9dc,0xb9febb5a,0xb94db64e,0x3bed3bdd,0x304eb1db,0xb2a1b807,0xbbd4bae9,0x39ba3b30,0x39963705,0x36aa2f0e,0xbb46bbf4,0x3115375e,0x3be63b1a,
0x39963ae9,0x39ba3807,0xbbddbb30,0x31db3705,0x336537b7,0x3bc93b02,0xbb80bbf8,0xb593ad7e,0xb4d5a8b6,0x3ba03bff,0xb900ba7c,0xba3fb8b0,0xb9feb85d,0x394d3ab5,0xb04eb64e,0xbbedbb5a,
0xabd9b475,0xbbfcbbaf,0x3bed3bf8,0x304ead7e,0x35f13115,0xbb6ebbe6,0x3ab53b80,0x385d3593,0x39dc3887,0xb972ba99,0x38323996,0x3ad039ba,0x3ba03ae9,0xb4d5b807,0x2f0e3534,0x3bf43b91,
0xb8d8b75e,0x3a5e3b1a,0xbb30bbaf,0xb705b475,0xbab5b9dc,0x385d3972,0xb996ba7c,0xb9bab8b0,0xbbc9bb5a,0x3365364e,0xb6aab887,0xbb46ba99,0xbbf4bbfc,0xaf0e2bd9,0xad7eb414,0xbbf8bbbc,
0x3bd43b91,0xb2a1b534,0x39ba3a5e,0x399638d8,0x3bff3bf8,0x28b6ad7e,0x38323900,0x3ad03a3f,0x3baf3be6,0x34753115,0x34d536aa,0x3ba03b46,0x3ae93b5a,0x3807364e,0x2bd931db,0x3bfc3bdd,
0xbb02bb46,0xb7b7b6aa,0xb75eb832,0xbb1abad0,0xba5ebab5,0xb8d8b85d,0xb534b64e,0xbb91bb5a,0xb996b9fe,0xb9bab94d,0xb1dbb414,0xbbddbbbc,0xb8b0b927,0xba7cba1f,0xa8b6af0e,0xbbffbbf4,
0x359335f1,0x3b803b6e,0x311531db,0x3be63bdd,0x34d53534,0x3ba03b91,0x2f0e304e,0x3bf43bed,0x34143475,0x3bbc3baf,0x2bd92d7e,0x3bfc3bf8,0x32a13365,0x3bd43bc9,0x224828b6,0x3c003bff,
0x40000,0x60002,0xc0008,0xe000a,0x380034,0x3a0036,0x40003c,0x42003e,0x6c0068,0x6e006a,0x740070,0x760072,0xa0009c,0xa2009e,0xa800a4,0xaa00a6,
0xd400d0,0xd600d2,0xdc00d8,0xde00da,0x1080104,0x10a0106,0x110010c,0x112010e,0x13c0138,0x13e013a,0x1440140,0x1460142,0x170016c,0x172016e,0x1780174,0x17a0176,
0x1a401a0,0x1a601a2,0x1ac01a8,0x1ae01aa,0x1d801d4,0x1da01d6,0x1e001dc,0x1e201de,0x20c0208,0x20e020a,0x2140210,0x2160212,0x240023c,0x242023e,0x2480244,0x24a0246,
0x2740270,0x2760272,0x27c0278,0x27e027a,0x2a802a4,0x2aa02a6,0x2b002ac,0x2b202ae,0x2dc02d8,0x2de02da,0x2e402e0,0x2e602e2,0x310030c,0x312030e,0x3180314,0x31a0316,
0x3440340,0x3460342,0x34c0348,0x34e034a,0x3780374,0x37a0376,0x380037c,0x382037e,0x3ac03a8,0x3ae03aa,0x3b403b0,0x3b603b2,0x3e003dc,0x3e203de,0x3e803e4,0x3ea03e6,
0x4140410,0x4160412,0x41c0418,0x41e041a,0x4480444,0x44a0446,0x450044c,0x452044e,0x47c0478,0x47e047a,0x4840480,0x4860482,0x4b004ac,0x4b204ae,0x4b804b4,0x4ba04b6,
0x4e404e0,0x4e604e2,0x4ec04e8,0x4ee04ea,0x5180514,0x51a0516,0x520051c,0x522051e,0x54c0548,0x54e054a,0x5540550,0x5560552,0x580057c,0x582057e,0x5880584,0x58a0586,
0x5b405b0,0x5b605b2,0x5bc05b8,0x5be05ba,0x5e805e4,0x5ea05e6,0x5f005ec,0x5f205ee,0x61c0618,0x61e061a,0x6240620,0x6260622,0x650064c,0x652064e,0x6580654,0x65a0656,
0x140010,0x160012,0x120010,0x440012,0x480044,0x4a0046,0x460044,0x780046,0x7c0078,0x7e007a,0x7a0078,0xac007a,0xb000ac,0xb200ae,0xae00ac,0xe000ae,
0xe400e0,0xe600e2,0xe200e0,0x11400e2,0x1180114,0x11a0116,0x1160114,0x1480116,0x14c0148,0x14e014a,0x14a0148,0x17c014a,0x180017c,0x182017e,0x17e017c,0x1b0017e,
0x1b401b0,0x1b601b2,0x1b201b0,0x1e401b2,0x1e801e4,0x1ea01e6,0x1e601e4,0x21801e6,0x21c0218,0x21e021a,0x21a0218,0x24c021a,0x250024c,0x252024e,0x24e024c,0x280024e,
0x2840280,0x2860282,0x2820280,0x2b40282,0x2b802b4,0x2ba02b6,0x2b602b4,0x2e802b6,0x2ec02e8,0x2ee02ea,0x2ea02e8,0x31c02ea,0x320031c,0x322031e,0x31e031c,0x350031e,
0x3540350,0x3560352,0x3520350,0x3840352,0x3880384,0x38a0386,0x3860384,0x3b80386,0x3bc03b8,0x3be03ba,0x3ba03b8,0x3ec03ba,0x3f003ec,0x3f203ee,0x3ee03ec,0x42003ee,
0x4240420,0x4260422,0x4220420,0x4540422,0x4580454,0x45a0456,0x4560454,0x4880456,0x48c0488,0x48e048a,0x48a0488,0x4bc048a,0x4c004bc,0x4c204be,0x4be04bc,0x4f004be,
0x4f404f0,0x4f604f2,0x4f204f0,0x52404f2,0x5280524,0x52a0526,0x5260524,0x5580526,0x55c0558,0x55e055a,0x55a0558,0x58c055a,0x590058c,0x592058e,0x58e058c,0x5c0058e,
0x5c405c0,0x5c605c2,0x5c205c0,0x5f405c2,0x5f805f4,0x5fa05f6,0x5f605f4,0x62805f6,0x62c0628,0x62e062a,0x62a0628,0x65c062a,0x660065c,0x662065e,0x65e065c,0x18065e,
0x180018,0x4c001a,0x1a0018,0x4c001a,0x4c004c,0x80004e,0x4e004c,0x80004e,0x800080,0xb40082,0x820080,0xb40082,0xb400b4,0xe800b6,0xb600b4,0xe800b6,
0xe800e8,0x11c00ea,0xea00e8,0x11c00ea,0x11c011c,0x150011e,0x11e011c,0x150011e,0x1500150,0x1840152,0x1520150,0x1840152,0x1840184,0x1b80186,0x1860184,0x1b80186,
0x1b801b8,0x1ec01ba,0x1ba01b8,0x1ec01ba,0x1ec01ec,0x22001ee,0x1ee01ec,0x22001ee,0x2200220,0x2540222,0x2220220,0x2540222,0x2540254,0x2880256,0x2560254,0x2880256,
0x2880288,0x2bc028a,0x28a0288,0x2bc028a,0x2bc02bc,0x2f002be,0x2be02bc,0x2f002be,0x2f002f0,0x32402f2,0x2f202f0,0x32402f2,0x3240324,0x3580326,0x3260324,0x3580326,
0x3580358,0x38c035a,0x35a0358,0x38c035a,0x38c038c,0x3c0038e,0x38e038c,0x3c0038e,0x3c003c0,0x3f403c2,0x3c203c0,0x3f403c2,0x3f403f4,0x42803f6,0x3f603f4,0x42803f6,
0x4280428,0x45c042a,0x42a0428,0x45c042a,0x45c045c,0x490045e,0x45e045c,0x490045e,0x4900490,0x4c40492,0x4920490,0x4c40492,0x4c404c4,0x4f804c6,0x4c604c4,0x4f804c6,
0x4f804f8,0x52c04fa,0x4fa04f8,0x52c04fa,0x52c052c,0x560052e,0x52e052c,0x560052e,0x5600560,0x5940562,0x5620560,0x5940562,0x5940594,0x5c80596,0x5960594,0x5c80596,
0x5c805c8,0x5fc05ca,0x5ca05c8,0x5fc05ca,0x5fc05fc,0x63005fe,0x5fe05fc,0x63005fe,0x6300630,0x6640632,0x6320630,0x6640632,0x6640664,0x1c0666,0x6660664,0x1c0666,
0x1c001c,0x50001e,0x1e001c,0x50001e,0x500050,0x840052,0x520050,0x840052,0x840084,0xb80086,0x860084,0xb80086,0xb800b8,0xec00ba,0xba00b8,0xec00ba,
0xec00ec,0x12000ee,0xee00ec,0x12000ee,0x1200120,0x1540122,0x1220120,0x1540122,0x1540154,0x1880156,0x1560154,0x1880156,0x1880188,0x1bc018a,0x18a0188,0x1bc018a,
0x1bc01bc,0x1f001be,0x1be01bc,0x1f001be,0x1f001f0,0x22401f2,0x1f201f0,0x22401f2,0x2240224,0x2580226,0x2260224,0x2580226,0x2580258,0x28c025a,0x25a0258,0x28c025a,
0x28c028c,0x2c0028e,0x28e028c,0x2c0028e,0x2c002c0,0x2f402c2,0x2c202c0,0x2f402c2,0x2f402f4,0x32802f6,0x2f602f4,0x32802f6,0x3280328,0x35c032a,0x32a0328,0x35c032a,
0x35c035c,0x390035e,0x35e035c,0x390035e,0x3900390,0x3c40392,0x3920390,0x3c40392,0x3c403c4,0x3f803c6,0x3c603c4,0x3f803c6,0x3f803f8,0x42c03fa,0x3fa03f8,0x42c03fa,
0x42c042c,0x460042e,0x42e042c,0x460042e,0x4600460,0x4940462,0x4620460,0x4940462,0x4940494,0x4c80496,0x4960494,0x4c80496,0x4c804c8,0x4fc04ca,0x4ca04c8,0x4fc04ca,
0x4fc04fc,0x53004fe,0x4fe04fc,0x53004fe,0x5300530,0x5640532,0x5320530,0x5640532,0x5640564,0x5980566,0x5660564,0x5980566,0x5980598,0x5cc059a,0x59a0598,0x5cc059a,
0x5cc05cc,0x60005ce,0x5ce05cc,0x60005ce,0x6000600,0x6340602,0x6020600,0x6340602,0x6340634,0x6680636,0x6360634,0x6680636,0x6680668,0x20066a,0x66a0668,0x20066a,
0x5d605d6,0x60a05d6,0x5d605d6,0x60a060a,0x60a060a,0x63e063e,0x60a060a,0x63e063e,0x63e063e,0x672063e,0x63e063e,0x6720672,0x6720672,0x280028,0x6720672,0x280028,
0x5060506,0x53a0506,0x5060506,0x53a053a,0x53a053a,0x56e056e,0x53a053a,0x56e056e,0x56e056e,0x5a2056e,0x56e056e,0x5a205a2,0x5a205a2,0x5d605d6,0x5a205a2,0x5d605d6,
0x4360436,0x46a0436,0x4360436,0x46a046a,0x46a046a,0x49e049e,0x46a046a,0x49e049e,0x49e049e,0x4d2049e,0x49e049e,0x4d204d2,0x4d204d2,0x5060506,0x4d204d2,0x5060506,
0x3660366,0x39a0366,0x3660366,0x39a039a,0x39a039a,0x3ce03ce,0x39a039a,0x3ce03ce,0x3ce03ce,0x40203ce,0x3ce03ce,0x4020402,0x4020402,0x4360436,0x4020402,0x4360436,
0x2960296,0x2ca0296,0x2960296,0x2ca02ca,0x2ca02ca,0x2fe02fe,0x2ca02ca,0x2fe02fe,0x2fe02fe,0x33202fe,0x2fe02fe,0x3320332,0x3320332,0x3660366,0x3320332,0x3660366,
0x1c601c6,0x1fa01c6,0x1c601c6,0x1fa01fa,0x1fa01fa,0x22e022e,0x1fa01fa,0x22e022e,0x22e022e,0x262022e,0x22e022e,0x2620262,0x2620262,0x2960296,0x2620262,0x2960296,
0xf600f6,0x12a00f6,0xf600f6,0x12a012a,0x12a012a,0x15e015e,0x12a012a,0x15e015e,0x15e015e,0x192015e,0x15e015e,0x1920192,0x1920192,0x1c601c6,0x1920192,0x1c601c6,
0x260026,0x5a0026,0x260026,0x5a005a,0x5a005a,0x8e008e,0x5a005a,0x8e008e,0x8e008e,0xc2008e,0x8e008e,0xc200c2,0xc200c2,0xf600f6,0xc200c2,0xf600f6,
0x5d405d4,0x60805d4,0x5d405d4,0x6080608,0x6080608,0x63c063c,0x6080608,0x63c063c,0x63c063c,0x670063c,0x63c063c,0x6700670,0x6700670,0x260026,0x6700670,0x260026,
0x5040504,0x5380504,0x5040504,0x5380538,0x5380538,0x56c056c,0x5380538,0x56c056c,0x56c056c,0x5a0056c,0x56c056c,0x5a005a0,0x5a005a0,0x5d405d4,0x5a005a0,0x5d405d4,
0x4340434,0x4680434,0x4340434,0x4680468,0x4680468,0x49c049c,0x4680468,0x49c049c,0x49c049c,0x4d0049c,0x49c049c,0x4d004d0,0x4d004d0,0x5040504,0x4d004d0,0x5040504,
0x3640364,0x3980364,0x3640364,0x3980398,0x3980398,0x3cc03cc,0x3980398,0x3cc03cc,0x3cc03cc,0x40003cc,0x3cc03cc,0x4000400,0x4000400,0x4340434,0x4000400,0x4340434,
0x2940294,0x2c80294,0x2940294,0x2c802c8,0x2c802c8,0x2fc02fc,0x2c802c8,0x2fc02fc,0x2fc02fc,0x33002fc,0x2fc02fc,0x3300330,0x3300330,0x3640364,0x3300330,0x3640364,
0x1c401c4,0x1f801c4,0x1c401c4,0x1f801f8,0x1f801f8,0x22c022c,0x1f801f8,0x22c022c,0x22c022c,0x260022c,0x22c022c,0x2600260,0x2600260,0x2940294,0x2600260,0x2940294,
0xf400f4,0x12800f4,0xf400f4,0x1280128,0x1280128,0x15c015c,0x1280128,0x15c015c,0x15c015c,0x190015c,0x15c015c,0x1900190,0x1900190,0x1c401c4,0x1900190,0x1c401c4,
0x240024,0x580024,0x240024,0x580058,0x580058,0x8c008c,0x580058,0x8c008c,0x8c008c,0xc0008c,0x8c008c,0xc000c0,0xc000c0,0xf400f4,0xc000c0,0xf400f4,
0x5d205d2,0x60605d2,0x5d205d2,0x6060606,0x6060606,0x63a063a,0x6060606,0x63a063a,0x63a063a,0x66e063a,0x63a063a,0x66e066e,0x66e066e,0x240024,0x66e066e,0x240024,
0x5020502,0x5360502,0x5020502,0x5360536,0x5360536,0x56a056a,0x5360536,0x56a056a,0x56a056a,0x59e056a,0x56a056a,0x59e059e,0x59e059e,0x5d205d2,0x59e059e,0x5d205d2,
0x4320432,0x4660432,0x4320432,0x4660466,0x4660466,0x49a049a,0x4660466,0x49a049a,0x49a049a,0x4ce049a,0x49a049a,0x4ce04ce,0x4ce04ce,0x5020502,0x4ce04ce,0x5020502,
0x3620362,0x3960362,0x3620362,0x3960396,0x3960396,0x3ca03ca,0x3960396,0x3ca03ca,0x3ca03ca,0x3fe03ca,0x3ca03ca,0x3fe03fe,0x3fe03fe,0x4320432,0x3fe03fe,0x4320432,
0x2920292,0x2c60292,0x2920292,0x2c602c6,0x2c602c6,0x2fa02fa,0x2c602c6,0x2fa02fa,0x2fa02fa,0x32e02fa,0x2fa02fa,0x32e032e,0x32e032e,0x3620362,0x32e032e,0x3620362,
0x1c201c2,0x1f601c2,0x1c201c2,0x1f601f6,0x1f601f6,0x22a022a,0x1f601f6,0x22a022a,0x22a022a,0x25e022a,0x22a022a,0x25e025e,0x25e025e,0x2920292,0x25e025e,0x2920292,
0xf200f2,0x12600f2,0xf200f2,0x1260126,0x1260126,0x15a015a,0x1260126,0x15a015a,0x15a015a,0x18e015a,0x15a015a,0x18e018e,0x18e018e,0x1c201c2,0x18e018e,0x1c201c2,
0x220022,0x560022,0x220022,0x560056,0x560056,0x8a008a,0x560056,0x8a008a,0x8a008a,0xbe008a,0x8a008a,0xbe00be,0xbe00be,0xf200f2,0xbe00be,0xf200f2,
0x5d005d0,0x60405d0,0x5d005d0,0x6040604,0x6040604,0x6380638,0x6040604,0x6380638,0x6380638,0x66c0638,0x6380638,0x66c066c,0x66c066c,0x220022,0x66c066c,0x220022,
0x5000500,0x5340500,0x5000500,0x5340534,0x5340534,0x5680568,0x5340534,0x5680568,0x5680568,0x59c0568,0x5680568,0x59c059c,0x59c059c,0x5d005d0,0x59c059c,0x5d005d0,
0x4300430,0x4640430,0x4300430,0x4640464,0x4640464,0x4980498,0x4640464,0x4980498,0x4980498,0x4cc0498,0x4980498,0x4cc04cc,0x4cc04cc,0x5000500,0x4cc04cc,0x5000500,
0x3600360,0x3940360,0x3600360,0x3940394,0x3940394,0x3c803c8,0x3940394,0x3c803c8,0x3c803c8,0x3fc03c8,0x3c803c8,0x3fc03fc,0x3fc03fc,0x4300430,0x3fc03fc,0x4300430,
0x2900290,0x2c40290,0x2900290,0x2c402c4,0x2c402c4,0x2f802f8,0x2c402c4,0x2f802f8,0x2f802f8,0x32c02f8,0x2f802f8,0x32c032c,0x32c032c,0x3600360,0x32c032c,0x3600360,
0x1c001c0,0x1f401c0,0x1c001c0,0x1f401f4,0x1f401f4,0x2280228,0x1f401f4,0x2280228,0x2280228,0x25c0228,0x2280228,0x25c025c,0x25c025c,0x2900290,0x25c025c,0x2900290,
0xf000f0,0x12400f0,0xf000f0,0x1240124,0x1240124,0x1580158,0x1240124,0x1580158,0x1580158,0x18c0158,0x1580158,0x18c018c,0x18c018c,0x1c001c0,0x18c018c,0x1c001c0,
0x200020,0x540020,0x200020,0x540054,0x540054,0x880088,0x540054,0x880088,0x880088,0xbc0088,0x880088,0xbc00bc,0xbc00bc,0xf000f0,0xbc00bc,0xf000f0,
0x30003000,0x30003000,0x30003000,0x30003000,0x30003000,0x30003000,0x30003000,0x30003000,0x0,0x0,0x0,0x0,0x0,0x0,0x0,0x0,
0x30003000,0x30003000,0x30003000,0x30003000,0x30003000,0x30003000,0x30003000,0x30003000,0x0,0x0,0x0,0x0,0x0,0x0,0x0,0x0,
0x2a1f2da8,0xaf64ada8,0xaa1fada8,0x2f642da8,0x2f643000,0xaa1f0000,0xaf64b000,0x2a1f8000,0x2f642da8,0x2a1f2da8,0xaf64ada8,0xaa1fada8,0x2a1f0000,0x2f643000,0xaa1f0000,0xaf64b000,
0x263e2c72,0xafd9aea7,0xa63eac72,0x2fd92ea7,0x2ea72fd9,0xac72a63e,0xaea7afd9,0x2c72263e,0x2fd92ea7,0x263e2c72,0xafd9aea7,0xa63eac72,0x2c72263e,0x2ea72fd9,0xac72a63e,0xaea7afd9,
0x2da80000,0xada80000,0x2da88000,0xada80000,0x2da83000,0xada8b000,0x2da83000,0xada8b000,0x2da83000,0xada8b000,0x2da83000,0xada8b000,0xada80000,0x2da88000,0xada80000,0x2da88000,
0x2f642a1f,0xaf64aa1f,0x2f642a1f,0xaf64aa1f,0x2a1f2f64,0xaa1faf64,0x2a1f2f64,0xaa1faf64,0x2a1f2f64,0xaa1faf64,0x2a1f2f64,0xaa1faf64,0xaf64aa1f,0x2f642a1f,0xaf64aa1f,0x2f642a1f,
0xaa1f2da8,0x2f642da8,0x2a1fada8,0xaf64ada8,0x2f640000,0xaa1fb000,0xaf640000,0x2a1f3000,0xaf64ada8,0xaa1f2da8,0x2f642da8,0x2a1fada8,0x2a1f3000,0x2f648000,0xaa1fb000,0xaf640000,
0xaea7263e,0x2c722fd9,0x2ea7a63e,0xac72afd9,0x2fd92c72,0x263eaea7,0xafd9ac72,0xa63e2ea7,0xac72afd9,0xaea7263e,0x2c722fd9,0x2ea7a63e,0xa63e2ea7,0x2fd92c72,0x263eaea7,0xafd9ac72,
0xada82da8,0xada82da8,0xada82da8,0xada82da8,0x2da8ada8,0x2da8ada8,0x2da8ada8,0x2da8ada8,0x2da82da8,0x2da82da8,0x2da82da8,0x2da82da8,0xada8ada8,0xada8ada8,0xada8ada8,0xada8ada8,
0x3000,0x3000,0x3000,0x80003000,0x8000b000,0x8000b000,0x8000b000,0x8000b000,0x30000000,0x30008000,0x30008000,0x30008000,0xb0000000,0xb0000000,0xb0000000,0xb0000000,
0x2ea7263e,0xac722fd9,0xaea7a63e,0x2c72afd9,0xafd92c72,0xa63eaea7,0x2fd9ac72,0x263e2ea7,0x2c72afd9,0x2ea7263e,0xac722fd9,0xaea7a63e,0x263e2ea7,0xafd92c72,0xa63eaea7,0x2fd9ac72,
0x2f64ada8,0x2a1f2da8,0xaf642da8,0xaa1fada8,0xaa1f3000,0xaf640000,0x2a1fb000,0x2f648000,0xaa1fada8,0x2f64ada8,0x2a1f2da8,0xaf642da8,0x2f640000,0xaa1f3000,0xaf640000,0x2a1fb000,
0xaa1f2f64,0x2a1faf64,0xaa1f2f64,0x2a1faf64,0x2f64aa1f,0xaf642a1f,0x2f64aa1f,0xaf642a1f,0xaf642a1f,0x2f64aa1f,0xaf642a1f,0x2f64aa1f,0xaa1f2f64,0x2a1faf64,0xaa1f2f64,0x2a1faf64,
0x2da80000,0xada80000,0x2da88000,0xada80000,0x2da8b000,0xada83000,0x2da8b000,0xada83000,0xada83000,0x2da8b000,0xada83000,0x2da8b000,0x2da88000,0xada80000,0x2da88000,0xada88000,
0xa63e2c72,0x2fd9aea7,0x263eac72,0xafd92ea7,0xaea72fd9,0x2c72a63e,0x2ea7afd9,0xac72263e,0xafd92ea7,0xa63e2c72,0x2fd9aea7,0x263eac72,0xac72263e,0xaea72fd9,0x2c72a63e,0x2ea7afd9,
0x2f64ada8,0x2a1fada8,0xaf642da8,0xaa1f2da8,0x2a1f0000,0x2f64b000,0xaa1f0000,0xaf643000,0xaa1f2da8,0x2f64ada8,0x2a1fada8,0xaf642da8,0xaf643000,0x2a1f8000,0x2f64b000,0xaa1f8000,
0xb0003000,0xb0003000,0xb0003000,0xb0003000,0xb0003000,0xb0003000,0xb0003000,0xb0003000,0x0,0x8000,0x8000,0x80008000,0x8000,0x8000,0x8000,0x8000,
0x80000000,0x80000000,0x80008000,0x80008000,0x80000000,0x80008000,0x80008000,0x80008000,0xb0003000,0xb0003000,0xb0003000,0xb0003000,0xb0003000,0xb0003000,0xb0003000,0xb0003000,
0xaa1f2da8,0x2f64ada8,0x2a1fada8,0xaf642da8,0xaf643000,0x2a1f0000,0x2f64b000,0xaa1f8000,0xaf642da8,0xaa1f2da8,0x2f64ada8,0x2a1fada8,0xaa1f0000,0xaf643000,0x2a1f0000,0x2f64b000,
0x2fd9aea7,0x263eac72,0xafd92ea7,0xa63e2c72,0x2c72a63e,0x2ea7afd9,0xac72263e,0xaea72fd9,0xa63e2c72,0x2fd9aea7,0x263eac72,0xafd92ea7,0xaea72fd9,0x2c72a63e,0x2ea7afd9,0xac72263e,
0xada80000,0x2da80000,0xada88000,0x2da80000,0xada83000,0x2da8b000,0xada83000,0x2da8b000,0xada83000,0x2da8b000,0xada83000,0x2da8b000,0x2da80000,0xada88000,0x2da88000,0xada88000,
0xaa1f2f64,0x2a1faf64,0xaa1f2f64,0x2a1faf64,0x2f64aa1f,0xaf642a1f,0x2f64aa1f,0xaf642a1f,0x2f64aa1f,0xaf642a1f,0x2f64aa1f,0xaf642a1f,0x2a1faf64,0xaa1f2f64,0x2a1faf64,0xaa1f2f64,
0x2a1f2da8,0xaf642da8,0xaa1fada8,0x2f64ada8,0xaf640000,0x2a1fb000,0x2f640000,0xaa1f3000,0x2f64ada8,0x2a1f2da8,0xaf642da8,0xaa1fada8,0xaa1f3000,0xaf648000,0x2a1fb000,0x2f640000,
0x2c72afd9,0x2ea7263e,0xac722fd9,0xaea7a63e,0x263e2ea7,0xafd92c72,0xa63eaea7,0x2fd9ac72,0xaea7a63e,0x2c72afd9,0x2ea7263e,0xac722fd9,0x2fd9ac72,0x263e2ea7,0xafd92c72,0xa63eaea7,
0x2da8ada8,0x2da8ada8,0x2da8ada8,0x2da8ada8,0xada82da8,0xada82da8,0xada82da8,0xada82da8,0x2da82da8,0x2da82da8,0x2da82da8,0x2da82da8,0xada8ada8,0xada8ada8,0xada8ada8,0xada8ada8,
0x80003000,0x80003000,0x80003000,0x3000,0xb000,0x8000b000,0xb000,0xb000,0xb0000000,0xb0008000,0xb0008000,0xb0008000,0x30000000,0x30000000,0x30000000,0x30008000,
0x2c722fd9,0x2ea7a63e,0xac72afd9,0xaea7263e,0x263eaea7,0xafd9ac72,0xa63e2ea7,0x2fd92c72,0xaea7263e,0x2c722fd9,0x2ea7a63e,0xac72afd9,0x2fd92c72,0x263eaea7,0xafd9ac72,0xa63e2ea7,
0xaf64ada8,0xaa1f2da8,0x2f642da8,0x2a1fada8,0x2a1f3000,0x2f648000,0xaa1fb000,0xaf648000,0x2a1fada8,0xaf64ada8,0xaa1f2da8,0x2f642da8,0xaf640000,0x2a1f3000,0x2f648000,0xaa1fb000,
0x2f642a1f,0xaf64aa1f,0x2f642a1f,0xaf64aa1f,0x2a1f2f64,0xaa1faf64,0x2a1f2f64,0xaa1faf64,0xaa1faf64,0x2a1f2f64,0xaa1faf64,0x2a1f2f64,0x2f642a1f,0xaf64aa1f,0x2f642a1f,0xaf64aa1f,
0xada80000,0x2da80000,0xada88000,0x2da88000,0xada8b000,0x2da83000,0xada8b000,0x2da83000,0x2da83000,0xada8b000,0x2da83000,0xada8b000,0xada88000,0x2da88000,0xada88000,0x2da80000,
0x2fd92ea7,0x263e2c72,0xafd9aea7,0xa63eac72,0x2c72263e,0x2ea72fd9,0xac72a63e,0xaea7afd9,0xa63eac72,0x2fd92ea7,0x263e2c72,0xafd9aea7,0xaea7afd9,0x2c72263e,0x2ea72fd9,0xac72a63e,
0xaf64ada8,0xaa1fada8,0x2f642da8,0x2a1f2da8,0xaa1f0000,0xaf64b000,0x2a1f0000,0x2f643000,0x2a1f2da8,0xaf64ada8,0xaa1fada8,0x2f642da8,0x2f643000,0xaa1f8000,0xaf64b000,0x2a1f0000,
0x80008000,0x80008000,0x80008000,0x80008000,0x80008000,0x80008000,0x80008000,0x80008000,0x30003000,0x30003000,0x30003000,0x30003000,0x30003000,0x30003000,0x30003000,0x30003000,
0x80008000,0x80008000,0x80008000,0x80008000,0x80008000,0x80008000,0x80008000,0x80008000,0x30003000,0x30003000,0x30003000,0x30003000,0x30003000,0x30003000,0x30003000,0x30003000,
0xaf64ada8,0xaa1fada8,0x2f642da8,0x2a1f2da8,0xaa1f8000,0xaf64b000,0x2a1f8000,0x2f643000,0x2a1f2da8,0xaf64ada8,0xaa1fada8,0x2f642da8,0x2f643000,0xaa1f0000,0xaf64b000,0x2a1f8000,
0xafd9aea7,0xa63eac72,0x2fd92ea7,0x263e2c72,0xac72a63e,0xaea7afd9,0x2c72263e,0x2ea72fd9,0x263e2c72,0xafd9aea7,0xa63eac72,0x2fd92ea7,0x2ea72fd9,0xac72a63e,0xaea7afd9,0x2c72263e,
0x2da83000,0xada8b000,0x2da83000,0xada8b000,0xada80000,0x2da88000,0xada80000,0x2da88000,0xada88000,0x2da88000,0xada80000,0x2da88000,0xada8b000,0x2da83000,0xada8b000,0x2da83000,
0x2a1f2f64,0xaa1faf64,0x2a1f2f64,0xaa1faf64,0xaf64aa1f,0x2f642a1f,0xaf64aa1f,0x2f642a1f,0xaf64aa1f,0x2f642a1f,0xaf64aa1f,0x2f642a1f,0xaa1faf64,0x2a1f2f64,0xaa1faf64,0x2a1f2f64,
0xaf64ada8,0xaa1f2da8,0x2f642da8,0x2a1fada8,0x2a1f3000,0x2f648000,0xaa1fb000,0xaf640000,0x2a1fada8,0xaf64ada8,0xaa1f2da8,0x2f642da8,0xaf648000,0x2a1f3000,0x2f648000,0xaa1fb000,
0xac72afd9,0xaea7263e,0x2c722fd9,0x2ea7a63e,0xa63e2ea7,0x2fd92c72,0x263eaea7,0xafd9ac72,0x2ea7a63e,0xac72afd9,0xaea7263e,0x2c722fd9,0xafd9ac72,0xa63e2ea7,0x2fd92c72,0x263eaea7,
0xada8ada8,0xada8ada8,0xada8ada8,0xada8ada8,0x2da82da8,0x2da82da8,0x2da82da8,0x2da82da8,0xada82da8,0xada82da8,0xada82da8,0xada82da8,0x2da8ada8,0x2da8ada8,0x2da8ada8,0x2da8ada8,
0xb0008000,0xb0000000,0xb0000000,0xb0000000,0x30008000,0x30008000,0x30008000,0x30008000,0x3000,0x3000,0x3000,0x80003000,0x8000b000,0x8000b000,0x8000b000,0x8000b000,
0xac722fd9,0xaea7a63e,0x2c72afd9,0x2ea7263e,0xa63eaea7,0x2fd9ac72,0x263e2ea7,0xafd92c72,0x2ea7263e,0xac722fd9,0xaea7a63e,0x2c72afd9,0xafd92c72,0xa63eaea7,0x2fd9ac72,0x263e2ea7,
0x2a1f2da8,0xaf642da8,0xaa1fada8,0x2f64ada8,0xaf648000,0x2a1fb000,0x2f648000,0xaa1f3000,0x2f64ada8,0x2a1f2da8,0xaf642da8,0xaa1fada8,0xaa1f3000,0xaf640000,0x2a1fb000,0x2f648000,
0xaf642a1f,0x2f64aa1f,0xaf642a1f,0x2f64aa1f,0xaa1f2f64,0x2a1faf64,0xaa1f2f64,0x2a1faf64,0x2a1faf64,0xaa1f2f64,0x2a1faf64,0xaa1f2f64,0xaf642a1f,0x2f64aa1f,0xaf642a1f,0x2f64aa1f,
0xada83000,0x2da8b000,0xada83000,0x2da8b000,0x2da88000,0xada80000,0x2da88000,0xada88000,0xada88000,0x2da88000,0xada80000,0x2da88000,0xada83000,0x2da8b000,0xada83000,0x2da8b000,
0xafd92ea7,0xa63e2c72,0x2fd9aea7,0x263eac72,0xac72263e,0xaea72fd9,0x2c72a63e,0x2ea7afd9,0x263eac72,0xafd92ea7,0xa63e2c72,0x2fd9aea7,0x2ea7afd9,0xac72263e,0xaea72fd9,0x2c72a63e,
0xaa1f2da8,0x2f64ada8,0x2a1fada8,0xaf642da8,0xaf643000,0x2a1f8000,0x2f64b000,0xaa1f8000,0xaf642da8,0xaa1f2da8,0x2f64ada8,0x2a1fada8,0xaa1f8000,0xaf643000,0x2a1f8000,0x2f64b000,
0x80008000,0x80000000,0x80000000,0x0,0x80000000,0x80000000,0x80000000,0x80000000,0xb0003000,0xb0003000,0xb0003000,0xb0003000,0xb0003000,0xb0003000,0xb0003000,0xb0003000,
0x3000b000,0x3000b000,0x3000b000,0x3000b000,0x3000b000,0x3000b000,0x3000b000,0x3000b000,0x80000000,0x80000000,0x80008000,0x80008000,0x80000000,0x80008000,0x80008000,0x80008000,
0x2f64ada8,0x2a1fada8,0xaf642da8,0xaa1f2da8,0x2a1f8000,0x2f64b000,0xaa1f8000,0xaf643000,0xaa1f2da8,0x2f64ada8,0x2a1fada8,0xaf642da8,0xaf643000,0x2a1f0000,0x2f64b000,0xaa1f8000,
0x263eac72,0xafd92ea7,0xa63e2c72,0x2fd9aea7,0x2ea7afd9,0xac72263e,0xaea72fd9,0x2c72a63e,0x2fd9aea7,0x263eac72,0xafd92ea7,0xa63e2c72,0x2c72a63e,0x2ea7afd9,0xac72263e,0xaea72fd9,
0xada83000,0x2da8b000,0xada83000,0x2da8b000,0x2da80000,0xada88000,0x2da88000,0xada88000,0x2da88000,0xada88000,0x2da80000,0xada88000,0x2da8b000,0xada83000,0x2da8b000,0xada83000,
0x2f64aa1f,0xaf642a1f,0x2f64aa1f,0xaf642a1f,0x2a1faf64,0xaa1f2f64,0x2a1faf64,0xaa1f2f64,0x2a1faf64,0xaa1f2f64,0x2a1faf64,0xaa1f2f64,0xaf642a1f,0x2f64aa1f,0xaf642a1f,0x2f64aa1f,
0x2f64ada8,0x2a1f2da8,0xaf642da8,0xaa1fada8,0xaa1f3000,0xaf648000,0x2a1fb000,0x2f640000,0xaa1fada8,0x2f64ada8,0x2a1f2da8,0xaf642da8,0x2f648000,0xaa1f3000,0xaf648000,0x2a1fb000,
0xaea7a63e,0x2c72afd9,0x2ea7263e,0xac722fd9,0x2fd9ac72,0x263e2ea7,0xafd92c72,0xa63eaea7,0xac722fd9,0xaea7a63e,0x2c72afd9,0x2ea7263e,0xa63eaea7,0x2fd9ac72,0x263e2ea7,0xafd92c72,
0xada8ada8,0xada8ada8,0xada8ada8,0xada8ada8,0x2da82da8,0x2da82da8,0x2da82da8,0x2da82da8,0x2da8ada8,0x2da8ada8,0x2da8ada8,0x2da8ada8,0xada82da8,0xada82da8,0xada82da8,0xada82da8,
0x30008000,0x30000000,0x30000000,0x30000000,0xb0008000,0xb0008000,0xb0008000,0xb0000000,0x80003000,0x80003000,0x80003000,0x3000,0xb000,0x8000b000,0xb000,0xb000,
0x2ea7a63e,0xac72afd9,0xaea7263e,0x2c722fd9,0xafd9ac72,0xa63e2ea7,0x2fd92c72,0x263eaea7,0x2c722fd9,0x2ea7a63e,0xac72afd9,0xaea7263e,0x263eaea7,0xafd9ac72,0xa63e2ea7,0x2fd92c72,
0xaa1f2da8,0x2f642da8,0x2a1fada8,0xaf64ada8,0x2f648000,0xaa1fb000,0xaf640000,0x2a1f3000,0xaf64ada8,0xaa1f2da8,0x2f642da8,0x2a1fada8,0x2a1f3000,0x2f648000,0xaa1fb000,0xaf648000,
0xaa1faf64,0x2a1f2f64,0xaa1faf64,0x2a1f2f64,0x2f642a1f,0xaf64aa1f,0x2f642a1f,0xaf64aa1f,0xaf64aa1f,0x2f642a1f,0xaf64aa1f,0x2f642a1f,0xaa1faf64,0x2a1f2f64,0xaa1faf64,0x2a1f2f64,
0x2da83000,0xada8b000,0x2da83000,0xada8b000,0xada88000,0x2da88000,0xada88000,0x2da80000,0x2da88000,0xada88000,0x2da80000,0xada80000,0x2da83000,0xada8b000,0x2da83000,0xada8b000,
0xa63eac72,0x2fd92ea7,0x263e2c72,0xafd9aea7,0xaea7afd9,0x2c72263e,0x2ea72fd9,0xac72a63e,0xafd9aea7,0xa63eac72,0x2fd92ea7,0x263e2c72,0xac72a63e,0xaea7afd9,0x2c72263e,0x2ea72fd9,
0x2a1f2da8,0xaf64ada8,0xaa1fada8,0x2f642da8,0x2f643000,0xaa1f8000,0xaf64b000,0x2a1f0000,0x2f642da8,0x2a1f2da8,0xaf64ada8,0xaa1fada8,0x2a1f8000,0x2f643000,0xaa1f8000,0xaf64b000,
0x3c003c00,0x3c003c00,0x3c003c00,0x3c003c00,0x3c003c00,0x3c003c00,0x3c003c00,0x3c003c00,0x80008000,0x80008000,0x80008000,0x80008000,0x80008000,0x80008000,0x80008000,0x80008000,
0x3bd93c00,0x3aa73b64,0x387239a8,0x323e361f,0xb23e0000,0xb872b61f,0xbaa7b9a8,0xbbd9bb64,0xb23e8000,0xb872b61f,0xbaa7b9a8,0xbbd9bb64,0xbbd9bc00,0xbaa7bb64,0xb872b9a8,0xb23eb61f,
0xbb64bc00,0xb61fb9a8,0x361f8000,0x3b6439a8,0x3b643c00,0x361f39a8,0xb61f0000,0xbb64b9a8,0x361f8000,0x3b6439a8,0x3b643c00,0x361f39a8,0xb61f8000,0xbb64b9a8,0xbb64bc00,0xb61fb9a8,
0x38728000,0x3bd93b64,0x323e39a8,0xbaa7b61f,0x3aa73c00,0xb23e361f,0xbbd9b9a8,0xb872bb64,0x3aa73c00,0xb23e361f,0xbbd9b9a8,0xb872bb64,0xb8728000,0xbbd9bb64,0xb23eb9a8,0x3aa7361f,
0xbc008000,0x3c008000,0xbc000000,0x3c008000,0xbc000000,0x3c008000,0xbc000000,0x3c008000,0x3c00,0x8000bc00,0x3c00,0x8000bc00,0x3c00,0x8000bc00,0x80003c00,0x8000bc00,
0xbbd98000,0x3aa7361f,0xb872b9a8,0x323e3b64,0x323ebc00,0xb8723b64,0x3aa7b9a8,0xbbd9361f,0xb23e3c00,0x3872bb64,0xbaa739a8,0x3bd9b61f,0xbbd90000,0x3aa7361f,0xb872b9a8,0x323e3b64,
0x3b648000,0xb61fb9a8,0xb61f3c00,0x3b64b9a8,0xbb648000,0x361f39a8,0x361fbc00,0xbb6439a8,0x361fbc00,0xbb6439a8,0x3b648000,0xb61fb9a8,0xb61f3c00,0x3b64b9a8,0xbb640000,0x361f39a8,
0xb8723c00,0x3bd9b61f,0xb23eb9a8,0xbaa73b64,0xbaa78000,0xb23e3b64,0x3bd9b9a8,0xb872b61f,0x3aa78000,0x323ebb64,0xbbd939a8,0x3872361f,0xb8723c00,0x3bd9b61f,0xb23eb9a8,0xbaa73b64,
0xbbd93c00,0xbaa73b64,0xb87239a8,0xb23e361f,0x323e8000,0x3872b61f,0x3aa7b9a8,0x3bd9bb64,0x323e8000,0x3872b61f,0x3aa7b9a8,0x3bd9bb64,0x3bd9bc00,0x3aa7bb64,0x3872b9a8,0x323eb61f,
0xbc003c00,0xbc003c00,0xbc003c00,0xbc003c00,0xbc003c00,0xbc003c00,0xbc003c00,0xbc003c00,0x80008000,0x80000000,0x80000000,0x80000000,0x80000000,0x80000000,0x0,0x80000000,
0xb8728000,0xbbd93b64,0xb23e39a8,0x3aa7b61f,0xbaa73c00,0x323e361f,0x3bd9b9a8,0x3872bb64,0xbaa73c00,0x323e361f,0x3bd9b9a8,0x3872bb64,0x38728000,0x3bd9bb64,0x323eb9a8,0xbaa7361f,
0x3b64bc00,0x361fb9a8,0xb61f8000,0xbb6439a8,0xbb643c00,0xb61f39a8,0x361f0000,0x3b64b9a8,0xb61f8000,0xbb6439a8,0xbb643c00,0xb61f39a8,0x361f8000,0x3b64b9a8,0x3b64bc00,0x361fb9a8,
0x3bd98000,0xbaa7361f,0x3872b9a8,0xb23e3b64,0xb23ebc00,0x38723b64,0xbaa7b9a8,0x3bd9361f,0x323e3c00,0xb872bb64,0x3aa739a8,0xbbd9b61f,0x3bd98000,0xbaa7361f,0x3872b9a8,0xb23e3b64,
0x3c008000,0xbc008000,0x3c000000,0xbc008000,0x3c000000,0xbc008000,0x3c000000,0xbc000000,0x80003c00,0xbc00,0x80003c00,0x8000bc00,0x80003c00,0xbc00,0x80003c00,0xbc00,
0x38723c00,0xbbd9b61f,0x323eb9a8,0x3aa73b64,0x3aa78000,0x323e3b64,0xbbd9b9a8,0x3872b61f,0xbaa78000,0xb23ebb64,0x3bd939a8,0xb872361f,0x38723c00,0xbbd9b61f,0x323eb9a8,0x3aa73b64,
0xbb640000,0x361fb9a8,0x361f3c00,0xbb64b9a8,0x3b648000,0xb61f39a8,0xb61fbc00,0x3b6439a8,0xb61fbc00,0x3b6439a8,0xbb640000,0x361fb9a8,0x361f3c00,0xbb64b9a8,0x3b648000,0xb61f39a8,
0x39a83c00,0xb9a80000,0xb9a8bc00,0x39a88000,0x39a83c00,0xb9a80000,0xb9a8bc00,0x39a88000,0xb9a88000,0xb9a8bc00,0x39a88000,0x39a83c00,0xb9a80000,0xb9a8bc00,0x39a88000,0x39a83c00,
0x38723c00,0xbbd9b61f,0x323eb9a8,0x3aa73b64,0xbaa70000,0xb23ebb64,0x3bd939a8,0xb872361f,0xbaa78000,0xb23ebb64,0x3bd939a8,0xb872361f,0xb872bc00,0x3bd9361f,0xb23e39a8,0xbaa7bb64,
0xb61fbc00,0x3b6439a8,0xbb640000,0x361fb9a8,0x361f3c00,0xbb64b9a8,0x3b648000,0xb61f39a8,0x3b648000,0xb61f39a8,0xb61fbc00,0x3b6439a8,0xbb648000,0x361fb9a8,0x361f3c00,0xbb64b9a8,
0x3bd98000,0xbaa7361f,0x3872b9a8,0xb23e3b64,0x323e3c00,0xb872bb64,0x3aa739a8,0xbbd9b61f,0x323e3c00,0xb872bb64,0x3aa739a8,0xbbd9b61f,0xbbd98000,0x3aa7b61f,0xb87239a8,0x323ebb64,
0xb9a88000,0xb9a83c00,0x39a88000,0x39a8bc00,0xb9a80000,0xb9a83c00,0x39a88000,0x39a8bc00,0xb9a83c00,0x39a88000,0x39a8bc00,0xb9a80000,0xb9a83c00,0x39a88000,0x39a8bc00,0xb9a88000,
0xb8728000,0xbbd93b64,0xb23e39a8,0x3aa7b61f,0x3aa7bc00,0xb23eb61f,0xbbd939a8,0xb8723b64,0xbaa73c00,0x323e361f,0x3bd9b9a8,0x3872bb64,0xb8728000,0xbbd93b64,0xb23e39a8,0x3aa7b61f,
0x361f8000,0x3b64b9a8,0x3b64bc00,0x361fb9a8,0xb61f8000,0xbb6439a8,0xbb643c00,0xb61f39a8,0x3b64bc00,0x361fb9a8,0xb61f8000,0xbb6439a8,0xbb643c00,0xb61f39a8,0x361f8000,0x3b64b9a8,
0xbbd93c00,0xbaa73b64,0xb87239a8,0xb23e361f,0xb23e8000,0xb872361f,0xbaa739a8,0xbbd93b64,0x323e8000,0x3872b61f,0x3aa7b9a8,0x3bd9bb64,0xbbd93c00,0xbaa73b64,0xb87239a8,0xb23e361f,
0xb8723c00,0x3bd9b61f,0xb23eb9a8,0xbaa73b64,0x3aa78000,0x323ebb64,0xbbd939a8,0x3872361f,0x3aa78000,0x323ebb64,0xbbd939a8,0x3872361f,0x3872bc00,0xbbd9361f,0x323e39a8,0x3aa7bb64,
0xb9a83c00,0x39a80000,0x39a8bc00,0xb9a88000,0xb9a83c00,0x39a88000,0x39a8bc00,0xb9a88000,0x39a88000,0x39a8bc00,0xb9a88000,0xb9a83c00,0x39a80000,0x39a8bc00,0xb9a88000,0xb9a83c00,
0xbbd98000,0x3aa7361f,0xb872b9a8,0x323e3b64,0xb23e3c00,0x3872bb64,0xbaa739a8,0x3bd9b61f,0xb23e3c00,0x3872bb64,0xbaa739a8,0x3bd9b61f,0x3bd98000,0xbaa7b61f,0x387239a8,0xb23ebb64,
0x361fbc00,0xbb6439a8,0x3b640000,0xb61fb9a8,0xb61f3c00,0x3b64b9a8,0xbb648000,0x361f39a8,0xbb648000,0x361f39a8,0x361fbc00,0xbb6439a8,0x3b648000,0xb61fb9a8,0xb61f3c00,0x3b64b9a8,
0x38728000,0x3bd93b64,0x323e39a8,0xbaa7b61f,0xbaa7bc00,0x323eb61f,0x3bd939a8,0x38723b64,0x3aa73c00,0xb23e361f,0xbbd9b9a8,0xb872bb64,0x38728000,0x3bd93b64,0x323e39a8,0xbaa7b61f,
0x39a88000,0x39a83c00,0xb9a88000,0xb9a8bc00,0x39a80000,0x39a83c00,0xb9a80000,0xb9a8bc00,0x39a83c00,0xb9a88000,0xb9a8bc00,0x39a88000,0x39a83c00,0xb9a88000,0xb9a8bc00,0x39a80000,
0x3bd93c00,0x3aa73b64,0x387239a8,0x323e361f,0x323e8000,0x3872361f,0x3aa739a8,0x3bd93b64,0xb23e8000,0xb872b61f,0xbaa7b9a8,0xbbd9bb64,0x3bd93c00,0x3aa73b64,0x387239a8,0x323e361f,
0xb61f8000,0xbb64b9a8,0xbb64bc00,0xb61fb9a8,0x361f8000,0x3b6439a8,0x3b643c00,0x361f39a8,0xbb64bc00,0xb61fb9a8,0x361f0000,0x3b6439a8,0x3b643c00,0x361f39a8,0xb61f8000,0xbb64b9a8,
0x0,0x0,0x0,0x0,0x0,0x0,0x0,0x0,0x3c003c00,0x3c003c00,0x3c003c00,0x3c003c00,0x3c003c00,0x3c003c00,0x3c003c00,0x3c003c00,
0x323e0000,0x3872361f,0x3aa739a8,0x3bd93b64,0x3bd93c00,0x3aa73b64,0x387239a8,0x323e361f,0x3bd93c00,0x3aa73b64,0x387239a8,0x323e361f,0xb23e0000,0xb872b61f,0xbaa7b9a8,0xbbd9bb64,
0xb61f0000,0xbb64b9a8,0xbb64bc00,0xb61fb9a8,0x361f0000,0x3b6439a8,0x3b643c00,0x361f39a8,0xbb64bc00,0xb61fb9a8,0x361f8000,0x3b6439a8,0x3b643c00,0x361f39a8,0xb61f0000,0xbb64b9a8,
0xbaa7bc00,0x323eb61f,0x3bd939a8,0x38723b64,0x38720000,0x3bd93b64,0x323e39a8,0xbaa7b61f,0x38728000,0x3bd93b64,0x323e39a8,0xbaa7b61f,0x3aa73c00,0xb23e361f,0xbbd9b9a8,0xb872bb64,
0x3c00,0x8000bc00,0x3c00,0x8000bc00,0x3c00,0x8000bc00,0x80003c00,0x8000bc00,0x3c000000,0xbc000000,0x3c008000,0xbc000000,0x3c008000,0xbc000000,0x3c008000,0xbc000000,
0xb23e3c00,0x3872bb64,0xbaa739a8,0x3bd9b61f,0xbbd90000,0x3aa7361f,0xb872b9a8,0x323e3b64,0x3bd90000,0xbaa7b61f,0x387239a8,0xb23ebb64,0xb23e3c00,0x3872bb64,0xbaa739a8,0x3bd9b61f,
0x361fbc00,0xbb6439a8,0x3b648000,0xb61fb9a8,0xb61f3c00,0x3b64b9a8,0xbb640000,0x361f39a8,0xbb640000,0x361f39a8,0x361fbc00,0xbb6439a8,0x3b640000,0xb61fb9a8,0xb61f3c00,0x3b64b9a8,
0x3aa78000,0x323ebb64,0xbbd939a8,0x3872361f,0xb8723c00,0x3bd9b61f,0xb23eb9a8,0xbaa73b64,0x3872bc00,0xbbd9361f,0x323e39a8,0x3aa7bb64,0x3aa70000,0x323ebb64,0xbbd939a8,0x3872361f,
0xb23e0000,0xb872361f,0xbaa739a8,0xbbd93b64,0xbbd93c00,0xbaa73b64,0xb87239a8,0xb23e361f,0xbbd93c00,0xbaa73b64,0xb87239a8,0xb23e361f,0x323e8000,0x3872b61f,0x3aa7b9a8,0x3bd9bb64,
0x0,0x8000,0x8000,0x8000,0x8000,0x8000,0x80008000,0x8000,0xbc003c00,0xbc003c00,0xbc003c00,0xbc003c00,0xbc003c00,0xbc003c00,0xbc003c00,0xbc003c00,
0x3aa7bc00,0xb23eb61f,0xbbd939a8,0xb8723b64,0xb8720000,0xbbd93b64,0xb23e39a8,0x3aa7b61f,0xb8728000,0xbbd93b64,0xb23e39a8,0x3aa7b61f,0xbaa73c00,0x323e361f,0x3bd9b9a8,0x3872bb64,
0x361f0000,0x3b64b9a8,0x3b64bc00,0x361fb9a8,0xb61f0000,0xbb6439a8,0xbb643c00,0xb61f39a8,0x3b64bc00,0x361fb9a8,0xb61f8000,0xbb6439a8,0xbb643c00,0xb61f39a8,0x361f0000,0x3b64b9a8,
0x323e3c00,0xb872bb64,0x3aa739a8,0xbbd9b61f,0x3bd98000,0xbaa7361f,0x3872b9a8,0xb23e3b64,0xbbd90000,0x3aa7b61f,0xb87239a8,0x323ebb64,0x323e3c00,0xb872bb64,0x3aa739a8,0xbbd9b61f,
0x80003c00,0xbc00,0x80003c00,0x8000bc00,0x80003c00,0xbc00,0x80003c00,0xbc00,0xbc000000,0x3c000000,0xbc008000,0x3c000000,0xbc008000,0x3c000000,0xbc008000,0x3c008000,
0xbaa78000,0xb23ebb64,0x3bd939a8,0xb872361f,0x38723c00,0xbbd9b61f,0x323eb9a8,0x3aa73b64,0xb872bc00,0x3bd9361f,0xb23e39a8,0xbaa7bb64,0xbaa70000,0xb23ebb64,0x3bd939a8,0xb872361f,
0xb61fbc00,0x3b6439a8,0xbb640000,0x361fb9a8,0x361f3c00,0xbb64b9a8,0x3b648000,0xb61f39a8,0x3b648000,0xb61f39a8,0xb61fbc00,0x3b6439a8,0xbb640000,0x361fb9a8,0x361f3c00,0xbb64b9a8,
0x39a80000,0x39a83c00,0xb9a80000,0xb9a8bc00,0x39a88000,0x39a83c00,0xb9a80000,0xb9a8bc00,0x39a83c00,0xb9a80000,0xb9a8bc00,0x39a88000,0x39a83c00,0xb9a80000,0xb9a8bc00,0x39a88000,
0x3aa70000,0x323e3b64,0xbbd9b9a8,0x3872b61f,0x38723c00,0xbbd9b61f,0x323eb9a8,0x3aa73b64,0x38723c00,0xbbd9b61f,0x323eb9a8,0x3aa73b64,0xbaa70000,0xb23ebb64,0x3bd939a8,0xb872361f,
0xbb640000,0x361fb9a8,0x361f3c00,0xbb64b9a8,0x3b640000,0xb61f39a8,0xb61fbc00,0x3b6439a8,0xb61fbc00,0x3b6439a8,0xbb640000,0x361fb9a8,0x361f3c00,0xbb64b9a8,0x3b648000,0xb61f39a8,
0xb23ebc00,0x38723b64,0xbaa7b9a8,0x3bd9361f,0x3bd90000,0xbaa7361f,0x3872b9a8,0xb23e3b64,0x3bd98000,0xbaa7361f,0x3872b9a8,0xb23e3b64,0x323e3c00,0xb872bb64,0x3aa739a8,0xbbd9b61f,
0xb9a83c00,0x39a88000,0x39a8bc00,0xb9a80000,0xb9a83c00,0x39a88000,0x39a8bc00,0xb9a88000,0x39a80000,0x39a8bc00,0xb9a80000,0xb9a83c00,0x39a88000,0x39a8bc00,0xb9a80000,0xb9a83c00,
0xbaa73c00,0x323e361f,0x3bd9b9a8,0x3872bb64,0xb8728000,0xbbd93b64,0xb23e39a8,0x3aa7b61f,0x38720000,0x3bd9bb64,0x323eb9a8,0xbaa7361f,0xbaa73c00,0x323e361f,0x3bd9b9a8,0x3872bb64,
0x3b64bc00,0x361fb9a8,0xb61f8000,0xbb6439a8,0xbb643c00,0xb61f39a8,0x361f8000,0x3b64b9a8,0xb61f0000,0xbb6439a8,0xbb643c00,0xb61f39a8,0x361f0000,0x3b64b9a8,0x3b64bc00,0x361fb9a8,
0x323e8000,0x3872b61f,0x3aa7b9a8,0x3bd9bb64,0xbbd93c00,0xbaa73b64,0xb87239a8,0xb23e361f,0x3bd9bc00,0x3aa7bb64,0x3872b9a8,0x323eb61f,0x323e0000,0x3872b61f,0x3aa7b9a8,0x3bd9bb64,
0xbaa70000,0xb23e3b64,0x3bd9b9a8,0xb872b61f,0xb8723c00,0x3bd9b61f,0xb23eb9a8,0xbaa73b64,0xb8723c00,0x3bd9b61f,0xb23eb9a8,0xbaa73b64,0x3aa78000,0x323ebb64,0xbbd939a8,0x3872361f,
0xb9a80000,0xb9a83c00,0x39a80000,0x39a8bc00,0xb9a88000,0xb9a83c00,0x39a80000,0x39a8bc00,0xb9a83c00,0x39a80000,0x39a8bc00,0xb9a88000,0xb9a83c00,0x39a88000,0x39a8bc00,0xb9a88000,
0x323ebc00,0xb8723b64,0x3aa7b9a8,0xbbd9361f,0xbbd90000,0x3aa7361f,0xb872b9a8,0x323e3b64,0xbbd98000,0x3aa7361f,0xb872b9a8,0x323e3b64,0xb23e3c00,0x3872bb64,0xbaa739a8,0x3bd9b61f,
0x3b640000,0xb61fb9a8,0xb61f3c00,0x3b64b9a8,0xbb640000,0x361f39a8,0x361fbc00,0xbb6439a8,0x361fbc00,0xbb6439a8,0x3b640000,0xb61fb9a8,0xb61f3c00,0x3b64b9a8,0xbb648000,0x361f39a8,
0x3aa73c00,0xb23e361f,0xbbd9b9a8,0xb872bb64,0x38728000,0x3bd93b64,0x323e39a8,0xbaa7b61f,0xb8720000,0xbbd9bb64,0xb23eb9a8,0x3aa7361f,0x3aa73c00,0xb23e361f,0xbbd9b9a8,0xb872bb64,
0x39a83c00,0xb9a88000,0xb9a8bc00,0x39a88000,0x39a83c00,0xb9a88000,0xb9a8bc00,0x39a80000,0xb9a80000,0xb9a8bc00,0x39a80000,0x39a83c00,0xb9a88000,0xb9a8bc00,0x39a88000,0x39a83c00,
0xb23e8000,0xb872b61f,0xbaa7b9a8,0xbbd9bb64,0x3bd93c00,0x3aa73b64,0x387239a8,0x323e361f,0xbbd9bc00,0xbaa7bb64,0xb872b9a8,0xb23eb61f,0xb23e0000,0xb872b61f,0xbaa7b9a8,0xbbd9bb64,
0xbb64bc00,0xb61fb9a8,0x361f0000,0x3b6439a8,0x3b643c00,0x361f39a8,0xb61f8000,0xbb64b9a8,0x361f0000,0x3b6439a8,0x3b643c00,0x361f39a8,0xb61f0000,0xbb64b9a8,0xbb64bc00,0xb61fb9a8,
};
__device__ __align__(1024) bf16 g_x1T[DM * XP];
__device__ __align__(1024) bf16 g_x2T[2][DM * XP];
__device__ __align__(1024) float g_fs[2][SEQ];

#define TS_SMEM 0
#define TS_DECL
#define TS_ARG
#define TS_PASS
#define TS_PHASE(p)
#define TS(i)
#define TSX(row, i)
#define TS_BEGIN
#define TS_END

struct cplx { float r, i; };
__device__ __forceinline__ cplx cmul(cplx a, cplx b) {
    cplx o;
    o.r = fmaf(a.r, b.r, -a.i * b.i);
    o.i = fmaf(a.r, b.i, a.i * b.r);
    return o;
}
__device__ __forceinline__ cplx csq(cplx a) {
    cplx o;
    o.r = fmaf(a.r, a.r, -a.i * a.i);
    o.i = 2.f * a.r * a.i;
    return o;
}
__device__ __forceinline__ cplx cexp_p(float arl, float ai, float p) {
    float mag = ex2(arl * p);
    float ang = ai * p;
    float n = rintf(ang * 0.15915494309189535f);
    float r = fmaf(n, -6.2831854820251465f, ang);
    r = fmaf(n, 1.7484555e-7f, r);
    cplx o;
    o.r = mag * __cosf(r);
    o.i = mag * __sinf(r);
    return o;
}

__device__ __forceinline__ uint32_t pack2h(float lo, float hi) {
    uint32_t r;
    asm("cvt.rn.f16x2.f32 %0, %1, %2;" : "=r"(r) : "f"(hi), "f"(lo));
    return r;
}
__device__ __forceinline__ uint32_t hmul(uint32_t a, uint32_t b) { uint32_t d; asm("mul.rn.f16x2 %0, %1, %2;" : "=r"(d) : "r"(a), "r"(b)); return d; }
__device__ __forceinline__ uint32_t hfma(uint32_t a, uint32_t b, uint32_t c) { uint32_t d; asm("fma.rn.f16x2 %0, %1, %2, %3;" : "=r"(d) : "r"(a), "r"(b), "r"(c)); return d; }
__device__ __forceinline__ uint32_t hfms(uint32_t a, uint32_t b, uint32_t c) {
    uint32_t d;
    asm("{\n.reg .b32 n;\nneg.f16x2 n, %1;\nfma.rn.f16x2 %0, n, %2, %3;\n}" : "=r"(d) : "r"(a), "r"(b), "r"(c));
    return d;
}
__device__ __forceinline__ uint32_t hadd(uint32_t a, uint32_t b) { uint32_t d; asm("add.rn.f16x2 %0, %1, %2;" : "=r"(d) : "r"(a), "r"(b)); return d; }
__device__ __forceinline__ uint32_t hsub(uint32_t a, uint32_t b) { uint32_t d; asm("sub.rn.f16x2 %0, %1, %2;" : "=r"(d) : "r"(a), "r"(b)); return d; }
__device__ __forceinline__ uint4 ldg_tab(int tab, int t) { return ldg128((const uint4*)c_fft + t + tab * 128); }
__device__ __forceinline__ uint32_t u4(const uint4& v, int i) { return i == 0 ? v.x : i == 1 ? v.y : i == 2 ? v.z : v.w; }
struct cpair { uint32_t r, i; };
__device__ __forceinline__ cpair pmul(cpair p, uint32_t z) {
    const __half2 zv = *reinterpret_cast<const __half2*>(&z), pr = *reinterpret_cast<const __half2*>(&p.r), pi = *reinterpret_cast<const __half2*>(&p.i);
    const __half2 zr = __low2half2(zv), zi = __high2half2(zv);
    const __half2 a = __hfma2(__hneg2(pi), zi, __hmul2(pr, zr)), b = __hfma2(pi, zr, __hmul2(pr, zi));
    return {*reinterpret_cast<const uint32_t*>(&a), *reinterpret_cast<const uint32_t*>(&b)};
}
__device__ __forceinline__ uint32_t packz(cplx z) { return pack2h(z.r, z.i); }
__device__ __forceinline__ void wgmma_kg(float (&d)[24], uint64_t da, uint64_t db, int scale_d) {
    asm volatile("{\n.reg .pred p;\nsetp.ne.b32 p, %26, 0;\n"
                 "wgmma.mma_async.sync.aligned.m64n48k16.f32.f16.f16 "
                 "{%0,%1,%2,%3,%4,%5,%6,%7,%8,%9,%10,%11,%12,%13,%14,%15,%16,%17,%18,%19,%20,%21,%22,%23}, %24, %25, p, 1, 1, 1, 1;\n}\n"
                 : "+f"(d[0]), "+f"(d[1]), "+f"(d[2]), "+f"(d[3]), "+f"(d[4]), "+f"(d[5]), "+f"(d[6]), "+f"(d[7]), "+f"(d[8]), "+f"(d[9]),
                   "+f"(d[10]), "+f"(d[11]), "+f"(d[12]), "+f"(d[13]), "+f"(d[14]), "+f"(d[15]), "+f"(d[16]), "+f"(d[17]), "+f"(d[18]), "+f"(d[19]),
                   "+f"(d[20]), "+f"(d[21]), "+f"(d[22]), "+f"(d[23])
                 : "l"(da), "l"(db), "r"(scale_d));
}

struct SsmParams { const bf16 *lar, *aim, *cre, *cim, *logdt, *dskip; };
constexpr int KG_TABLES = 6 * 16384, KG_RES = 1664;
struct KgShared { uint32_t kmax[6], kexp[6]; float cinv[6]; };
struct KgParams { uint32_t l[3], a[3], r[3], i[3], dt, ds; };

__device__ __forceinline__ bool kg_is_hi(int warp) { return ((warp >> 1) ^ (warp >> 2)) & 1; }
__device__ __forceinline__ void kgen_load(KgParams& kp, int d0, int warp, int lane, const SsmParams& sp) {
    const int d = d0 + min(2 * (warp >> 2) + (warp & 1), 4), idx = d * (NMODE / 2) + lane;
    const bf16 *pr = kg_is_hi(warp) ? sp.cre : sp.lar, *pi = kg_is_hi(warp) ? sp.cim : sp.aim;
    kp.dt = __ldg((const uint16_t*)sp.logdt + d);
#pragma unroll
    for (int j = 0; j < 3; j++) {
        kp.l[j] = __ldg((const uint32_t*)sp.lar + idx + 32 * j); kp.a[j] = __ldg((const uint32_t*)sp.aim + idx + 32 * j);
        kp.r[j] = __ldg((const uint32_t*)pr + idx + 32 * j); kp.i[j] = __ldg((const uint32_t*)pi + idx + 32 * j);
    }
    kp.ds = __ldg((const uint16_t*)sp.dskip + d0 + min(warp >> 1, 4));
}

struct KgAnchors { uint32_t v[8]; };
__device__ __forceinline__ KgAnchors kg_anchor_lo(const KgParams& kp, uint32_t sel, float dt) {
    auto B = [&](uint32_t v) { return __uint_as_float(__byte_perm(v, 0u, sel)); };
    const float arl = -rbf(ex2(B(kp.l[0]) * 1.4426950408889634f)) * dt * 1.4426950408889634f, ai = B(kp.a[0]) * dt;
    const cplx z8 = cexp_p(arl, ai, 8.f), z16 = csq(z8), z24 = cmul(z16, z8), z32 = csq(z16), z64 = csq(z32), z128 = csq(z64), z192 = cmul(z128, z64);
    return {{pack2h(1.f, z8.r), pack2h(0.f, z8.i), pack2h(z16.r, z24.r), pack2h(z16.i, z24.i), packz(z32), packz(z64), packz(z128), packz(z192)}};
}
__device__ __forceinline__ KgAnchors kg_anchor_hi(const KgParams& kp, uint32_t sel, float dt, float cs) {
    auto B = [&](uint32_t v) { return __uint_as_float(__byte_perm(v, 0u, sel)); };
    const float arl = -rbf(ex2(B(kp.l[0]) * 1.4426950408889634f)) * dt * 1.4426950408889634f, ai = B(kp.a[0]) * dt;
    const cplx z1 = cexp_p(arl, -ai, 1.f), z2 = csq(z1), z4 = csq(z2), z256 = cexp_p(arl, -ai, 256.f), z512 = csq(z256), z1024 = csq(z512);
    const cplx H0 = {B(kp.r[0]) * cs, -B(kp.i[0]) * cs}, H4 = cmul(H0, z4);
    return {{pack2h(H0.r, H4.r), pack2h(H0.i, H4.i), packz(z1), packz(z2), packz(z256), packz(z512), packz(z1024), 0u}};
}

__device__ __forceinline__ void kgen_tables(KgParams& kp, uint32_t scr, uint32_t dump, KgShared* ks, int warp, int lane TS_ARG) {
    const int wg = warp >> 2, half = warp & 1, sw = lane & 7;
    const bool hi = kg_is_hi(warp);
    TS(23);
    const float dt = rbf(ex2(bf_lo(kp.dt) * 1.4426950408889634f));
    uint32_t sel = (wg == 2 && half) ? 0x3244u : 0x1044u;
    float cs = 0.f;
    KgAnchors an;
    if (hi) {
        uint32_t m = 0;
#pragma unroll
        for (int j = 0; j < 3; j++) m = __vmaxu2(m, __vmaxu2(kp.r[j] & 0x7FFF7FFFu, kp.i[j] & 0x7FFF7FFFu));
        m = __reduce_max_sync(~0u, max(m << 16, m & 0xFFFF0000u));
        const uint32_t e = min(max(__float_as_uint(2.f * dt * __uint_as_float(m)) >> 23, 2u), 252u);
        cs = 2.f * dt * __uint_as_float((253u - e) << 23);
        if (lane == 0) { ks->cinv[2 * wg + half] = __uint_as_float((e + 1u) << 23); ks->kmax[2 * wg + half] = 0u; }
        an = kg_anchor_hi(kp, sel, dt, cs);
    } else {
        an = kg_anchor_lo(kp, sel, dt);
    }
    float acc[24];
#pragma unroll
    for (int i = 0; i < 24; i++) acc[i] = 0.f;
    uint32_t tb = scr + 2 * wg * 16384 + lane * 128;
    uint64_t da = mkdesc(scr + 2 * wg * 16384, 4096, 1024, 1);
    int flip = 16384;
#pragma unroll 1
    for (int c = wg == 2 ? 1 : 0, step = wg == 2 ? 2 : 1; c < 6; c += step) {
        if (wg < 2) sel ^= 0x2200u;
        if (!hi) {
            if (c & 1) { kp.l[0] = kp.l[1]; kp.l[1] = kp.l[2]; kp.a[0] = kp.a[1]; kp.a[1] = kp.a[2]; }
            cpair p[4];
            p[0] = {an.v[0], an.v[1]}; p[1] = {an.v[2], an.v[3]};
            p[2] = pmul(p[0], an.v[4]); p[3] = pmul(p[1], an.v[4]);
#pragma unroll
            for (int j = 0; j < 4; j++) {
                cpair v[4];
#pragma unroll
                for (int i = 0; i < 4; i++) v[i] = j ? pmul(p[i], an.v[4 + j]) : p[i];
                const uint32_t a = tb + (((4 * half + j) ^ sw) << 4);
                sts128(a, make_uint4(v[0].r, v[1].r, v[2].r, v[3].r));
                sts128(a + 4096, make_uint4(v[0].i, v[1].i, v[2].i, v[3].i));
            }
            an = kg_anchor_lo(kp, sel, dt);
        } else {
            if (c & 1) {
#pragma unroll
                for (int j = 0; j < 2; j++) { kp.l[j] = kp.l[j + 1]; kp.a[j] = kp.a[j + 1]; kp.r[j] = kp.r[j + 1]; kp.i[j] = kp.i[j + 1]; }
            }
            const uint32_t h1 = an.v[2], h2 = an.v[3], h256 = an.v[4], h512 = an.v[5], h1024 = an.v[6];
            cpair p[11];
            p[0] = {an.v[0], an.v[1]};
            p[1] = pmul(p[0], h2); p[2] = pmul(p[0], h1); p[3] = pmul(p[1], h1);
            p[4] = pmul(p[0], h256); p[5] = pmul(p[1], h256); p[6] = pmul(p[0], h512); p[7] = pmul(p[4], h512);
            p[8] = pmul({__byte_perm(p[0].r, p[4].r, 0x5410), __byte_perm(p[0].i, p[4].i, 0x5410)}, h1024);
            p[9] = pmul(p[8], h512); p[10] = pmul(p[8], h1024);
#pragma unroll
            for (int j = 0; j < 3; j++) {
                const uint32_t a = tb + 8192 + (((3 * half + j) ^ sw) << 4);
                sts128(a, make_uint4(p[4 * j].r, p[4 * j + 1].r, p[4 * j + 2].r, p[j < 2 ? 4 * j + 3 : 10].r));
                sts128(a + 4096, make_uint4(p[4 * j].i, p[4 * j + 1].i, p[4 * j + 2].i, p[j < 2 ? 4 * j + 3 : 10].i));
            }
            an = kg_anchor_hi(kp, sel, dt, cs);
        }
        if (c == 0) TS(24);
        if (c == 3) TS(25);
        fence_async_smem();
        wg_wait<0>();
        named_bar(5 + wg, 128);
        wg_fence();
#pragma unroll
        for (int k = 0; k < 4; k++) wgmma_kg(acc, da + k * 128, da + 512 + k * 128, 1);
        wg_commit();
        tb += flip; da += flip >> 4; flip = -flip;
    }
    const bool up = warp & 2;
    const int r = 2 * wg + up, lo0 = 16 * half + (lane >> 2);
    const uint32_t o = dump + r * KG_RES + lo0 * 52 + 4 * (lane & 3);
    const float ci = __uint_as_float(lds32(s2u(&ks->cinv[r])));
    const float ds = (lane == 0 && warp <= 8 && !half) ? bf_lo(kp.ds) : 0.f;
    TS(26);
    wg_wait<0>();
    float v[12], m = 0.f;
#pragma unroll
    for (int j = 0; j < 12; j++) { v[j] = fmaf(ci, up ? acc[12 + j] : acc[j], j ? 0.f : ds); m = fmaxf(m, fabsf(v[j])); }
    const uint32_t mm = __reduce_max_sync(~0u, __float_as_uint(m));
    if (lane == 0) asm volatile("red.shared.max.u32 [%0], %1;" ::"r"(s2u(&ks->kmax[r])), "r"(mm) : "memory");
    named_bar(5 + wg, 128);
    const float mx = __uint_as_float(lds32(s2u(&ks->kmax[r]))) + (wg == 2 ? __uint_as_float(lds32(s2u(&ks->kmax[r ^ 1]))) : 0.f);
    const uint32_t e = min(max(__float_as_uint(mx) >> 23, 4u), 250u);
    const float sc = __uint_as_float((253u - e) << 23);
    if (lane == 0) ks->kexp[r] = e;
#pragma unroll
    for (int j = 0; j < 6; j++) sts32(o + (j & 1) * 416 + (j >> 1) * 16, pack2h(v[2 * j] * sc, v[2 * j + 1] * sc));
}
#define F_PPOS 0
#define F_STAG 4
__device__ __forceinline__ void wgmma_h64_rs(uint32_t (&d)[16], const uint4& a, uint64_t db, int scale_d) {
    asm volatile("{\n.reg .pred p;\nsetp.ne.b32 p, %21, 0;\n"
                 "wgmma.mma_async.sync.aligned.m64n64k16.f16.f16.f16 {%0,%1,%2,%3,%4,%5,%6,%7,%8,%9,%10,%11,%12,%13,%14,%15}, {%16,%17,%18,%19}, %20, p, 1, 1, 1;\n}\n"
                 : "+r"(d[0]), "+r"(d[1]), "+r"(d[2]), "+r"(d[3]), "+r"(d[4]), "+r"(d[5]), "+r"(d[6]), "+r"(d[7]), "+r"(d[8]), "+r"(d[9]),
                   "+r"(d[10]), "+r"(d[11]), "+r"(d[12]), "+r"(d[13]), "+r"(d[14]), "+r"(d[15])
                 : "r"(a.x), "r"(a.y), "r"(a.z), "r"(a.w), "l"(db), "r"(scale_d));
}
template <int TB>
__device__ __forceinline__ void wgmma_h32_rs(uint32_t (&d)[8], const uint4& a, uint64_t db, int scale_d) {
    asm volatile("{\n.reg .pred p;\nsetp.ne.b32 p, %13, 0;\n"
                 "wgmma.mma_async.sync.aligned.m64n32k16.f16.f16.f16 {%0,%1,%2,%3,%4,%5,%6,%7}, {%8,%9,%10,%11}, %12, p, 1, 1, %14;\n}\n"
                 : "+r"(d[0]), "+r"(d[1]), "+r"(d[2]), "+r"(d[3]), "+r"(d[4]), "+r"(d[5]), "+r"(d[6]), "+r"(d[7])
                 : "r"(a.x), "r"(a.y), "r"(a.z), "r"(a.w), "l"(db), "r"(scale_d), "n"(TB));
}
__device__ __forceinline__ void wgmma_s1(uint32_t (&d)[16], const uint4& a, uint64_t db, int scale_d) { wgmma_h64_rs(d, a, db, scale_d); }
__device__ __forceinline__ void wgmma_s1(uint32_t (&d)[8], const uint4& a, uint64_t db, int scale_d) { wgmma_h32_rs<1>(d, a, db, scale_d); }
__device__ __forceinline__ void wgmma_s4(float (&d)[32], const uint4& a, uint64_t db, uint32_t meta, int scale_d) {
    asm volatile("{\n.reg .pred p;\nsetp.ne.b32 p, %38, 0;\n"
                 "wgmma.mma_async.sp.sync.aligned.m64n64k32.f32.f16.f16 {%0,%1,%2,%3,%4,%5,%6,%7,%8,%9,%10,%11,%12,%13,%14,%15,%16,%17,%18,%19,%20,%21,%22,%23,%24,%25,%26,%27,%28,%29,%30,%31}, {%32,%33,%34,%35}, %36, %37, 0, p, 1, 1, 1;\n}\n"
                 : "+f"(d[0]), "+f"(d[1]), "+f"(d[2]), "+f"(d[3]), "+f"(d[4]), "+f"(d[5]), "+f"(d[6]), "+f"(d[7]), "+f"(d[8]), "+f"(d[9]), "+f"(d[10]), "+f"(d[11]), "+f"(d[12]), "+f"(d[13]), "+f"(d[14]), "+f"(d[15]), "+f"(d[16]), "+f"(d[17]), "+f"(d[18]), "+f"(d[19]), "+f"(d[20]), "+f"(d[21]), "+f"(d[22]), "+f"(d[23]), "+f"(d[24]), "+f"(d[25]), "+f"(d[26]), "+f"(d[27]), "+f"(d[28]), "+f"(d[29]), "+f"(d[30]), "+f"(d[31])
                 : "r"(a.x), "r"(a.y), "r"(a.z), "r"(a.w), "l"(db), "r"(meta), "r"(scale_d));
}
__device__ __forceinline__ void wgmma_s4(float (&d)[16], const uint4& a, uint64_t db, uint32_t meta, int scale_d) {
    asm volatile("{\n.reg .pred p;\nsetp.ne.b32 p, %22, 0;\n"
                 "wgmma.mma_async.sp.sync.aligned.m64n32k32.f32.f16.f16 {%0,%1,%2,%3,%4,%5,%6,%7,%8,%9,%10,%11,%12,%13,%14,%15}, {%16,%17,%18,%19}, %20, %21, 0, p, 1, 1, 1;\n}\n"
                 : "+f"(d[0]), "+f"(d[1]), "+f"(d[2]), "+f"(d[3]), "+f"(d[4]), "+f"(d[5]), "+f"(d[6]), "+f"(d[7]), "+f"(d[8]), "+f"(d[9]), "+f"(d[10]), "+f"(d[11]), "+f"(d[12]), "+f"(d[13]), "+f"(d[14]), "+f"(d[15])
                 : "r"(a.x), "r"(a.y), "r"(a.z), "r"(a.w), "l"(db), "r"(meta), "r"(scale_d));
}

__device__ __forceinline__ uint32_t& u4r(uint4& v, int i) { return i == 0 ? v.x : i == 1 ? v.y : i == 2 ? v.z : v.w; }

template <int NC>
__device__ __forceinline__ void fft_stage(const uint32_t (&u)[2][4], int c, uint32_t eo, int w, int lane) {
    const int mi = lane >> 3, mj = lane & 7;
    const uint32_t a = eo + (8 * w + mj) * 128 + (((4 * c + mi) ^ mj) << 4);
    stsm_x4(a, hadd(u[0][0], u[1][0]), hadd(u[0][1], u[1][1]), hadd(u[0][2], u[1][2]), hadd(u[0][3], u[1][3]));
    stsm_x4(NC == 2 ? a + 4096 : a ^ 64, hsub(u[0][0], u[1][0]), hsub(u[0][1], u[1][1]), hsub(u[0][2], u[1][2]), hsub(u[0][3], u[1][3]));
}
template <int NC>
__device__ __forceinline__ void kernel_stage(const uint4 (&ko)[2], uint32_t kt, uint32_t eo, int w, int lane) {
    uint32_t u[2][2][4];
#pragma unroll
    for (int h = 0; h < 2; h++)
#pragma unroll
        for (int j = 0; j < 4; j++) {
            const uint32_t a0 = kt + (u4(ko[h], j) & 0xFFFF), a1 = kt + (u4(ko[h], j) >> 16);
#pragma unroll
            for (int c = 0; c < 2; c++)
                asm volatile("{\n.reg .b16 a, b;\nld.shared.b16 a, [%1];\nld.shared.b16 b, [%2];\nmov.b32 %0, {a, b};\n}"
                             : "=r"(u[c][h][j]) : "r"(a0 + c * KG_RES), "r"(a1 + c * KG_RES) : "memory");
            if (NC == 1) u[0][h][j] = hadd(u[0][h][j], u[1][h][j]);
        }
#pragma unroll
    for (int c = 0; c < NC; c++) fft_stage<NC>(u[c], c, eo, w, lane);
}

template <int NC, bool SHEAR, class Mid>
__device__ __forceinline__ void fft_forward(const uint4 (&a1)[4], const uint4 (&tw)[4], uint32_t eo, uint32_t s2, uint32_t (&X)[NC][2][8], Mid mid) {
    uint32_t dr[8 * NC], di[8 * NC];
    const uint64_t de = mkdesc(eo, 4096, 1024, 1), d2 = mkdesc(s2, 16, 1024, 1);
    wg_fence();
    wgmma_s1(dr, a1[0], de, 0);
    wgmma_s1(di, a1[2], de + (NC == 2 ? 256 : 4), 0);
    wgmma_s1(dr, a1[1], de + 128, 1);
    wgmma_s1(di, a1[3], de + (NC == 2 ? 384 : 132), 1);
    wg_commit();
    mid();
    wg_wait<0>();
#pragma unroll
    for (int c = 0; c < NC; c++) {
        uint4 zr[2], zi[2];
#pragma unroll
        for (int p = 0; p < 2; p++)
#pragma unroll
            for (int i = 0; i < 4; i++) {
                const uint32_t r = dr[8 * c + 4 * p + i], m = di[8 * c + 4 * p + i], tr = u4(tw[p], i), ti = u4(tw[2 + p], i);
                if (SHEAR) {
                    const uint32_t r1 = hfma(tr, m, r), m1 = hfma(ti, r1, m);
                    u4r(zr[p], i) = hfma(tr, m1, r1); u4r(zi[p], i) = m1;
                } else {
                    u4r(zr[p], i) = hfms(m, ti, hmul(r, tr));
                    u4r(zi[p], i) = hfma(m, tr, hmul(r, ti));
                }
            }
        wg_fence();
        wgmma_h32_rs<0>(X[c][0], zi[0], d2 + 2, 0);
        wgmma_h32_rs<0>(X[c][1], zi[1], d2 + 6, 0);
        wgmma_h32_rs<0>(X[c][0], zr[0], d2, 1);
        wgmma_h32_rs<0>(X[c][1], zr[1], d2 + 4, 1);
        wg_commit();
    }
}

template <int NC, class Idle, class Ready, class Staged>
__device__ __forceinline__ void conv_wg(int ch0, int layer, uint32_t eo, uint32_t zb, uint32_t s23, uint32_t kexp, uint32_t st, uint32_t sbar,
                                        int warp, int lane, uint4 (&a1)[4], uint4 (&tw)[4], Idle idle, Ready ready, Staged staged TS_ARG) {
    const int wg = warp >> 2, w = warp & 3, t = 32 * w + lane, g = lane >> 2, q = lane & 3, mi = lane >> 3, mj = lane & 7;
    auto F = [](uint32_t x) { return __uint_as_float(x); };
    uint32_t KH[NC][2][8];
    TS(2);
    fft_forward<NC, false>(a1, tw, eo, s23, KH, [] {});
    named_bar(1 + wg, 128);
    uint4 a4[4];
#pragma unroll
    for (int i = 0; i < 4; i++) { tw[i] = ldg_tab(4 + i, t); if (NC == 2) a4[i] = ldg_tab(12 + i, t); }
    wg_wait<0>();
    TS(4);
    idle();
    uint2 x[NC][2][2];
    const int ra[2] = {16 * (8 * w + g) + 4 * q, 16 * (63 - 8 * w - g) + 4 * q};
    if (NC == 1) {
        uint4 s[8];
        TS(1);
#pragma unroll
        for (int i = 0; i < 8; i++) s[i] = make_uint4(layer, 0, 0, 0);
        int spin = 0;
        uint32_t bad;
        do {
            bad = 0;
#pragma unroll
            for (int i = 0; i < 8; i++)
                if (((s[i].x ^ layer) & 1u) == 0) s[i] = ld_ll4((const uint4*)(g_fs[i & 1] + 1024 * ((i >> 1) & 1) + ra[i >> 2]));
#pragma unroll
            for (int i = 0; i < 8; i++) bad |= ~(s[i].x ^ layer);
        } while ((bad & 1u) && ++spin < (1 << 18));
#pragma unroll
        for (int i = 0; i < 8; i++) sts128(st + i * 2048 + t * 16, s[i]);
        __syncwarp();
        if (lane == 0) mbar_arrive(sbar + 8 * w);
#pragma unroll
        for (int i = 0; i < 4; i++) a4[i] = ldg_tab(12 + i, t);
        TS(14);
    }
    ready();
    TS(5);
#pragma unroll
    for (int i = 0; i < 4 * NC; i++) x[i >> 2][(i >> 1) & 1][i & 1] = ldg64(g_x1T + (size_t)(ch0 + (i >> 2)) * XP + 1024 * (i & 1) + ra[(i >> 1) & 1]);
    if (F_PPOS == 0) staged();
    TS(6);
    if (NC == 2) mbar_wait(sbar + 8 * w, 0);
    {
        uint4 s[2][2][2];
        uint32_t u[NC][2][4];
#pragma unroll
        for (int h = 0; h < 2; h++) {
            if (NC == 1 || h == 0) {
#pragma unroll
                for (int i = 4 * h; i < (NC == 1 ? 4 * h + 4 : 8); i++) s[i >> 2][(i >> 1) & 1][i & 1] = lds128(st + i * 2048 + t * 16);
            }
            if (h == 0) TS(7);
#pragma unroll
            for (int c = 0; c < NC; c++)
#pragma unroll
                for (int j = 0; j < 4; j++) {
                    const uint4 &a = s[h][j >> 1][0], &b = s[h][j >> 1][1];
                    const uint32_t xv = (j & 1) ? x[c][h][j >> 1].y : x[c][h][j >> 1].x;
                    u[c][h][j] = pack2h(fmaf(bf_lo(xv), F(u4(a, 2 * (j & 1))), F(u4(b, 2 * (j & 1)))), fmaf(bf_hi(xv), F(u4(a, 2 * (j & 1) + 1)), F(u4(b, 2 * (j & 1) + 1))));
                }
        }
#pragma unroll
        for (int c = 0; c < NC; c++) fft_stage<NC>(u[c], c, eo, w, lane);
    }
    TS(8);
    fence_async_smem();
    TS(9);
    if (F_PPOS == 1) staged();
    named_bar(1 + wg, 128);
    uint32_t X[NC][2][8], Y[NC][2][8];
    fft_forward<NC, true>(a1, tw, eo, s23, X, [&] { TS(3); if (F_PPOS == 2) staged(); if (F_STAG >= 2 && NC == 2 && wg == 1) named_bar(10 + w, 64); });
    if (F_STAG == 2 && NC == 2 && wg == 0) asm volatile("bar.arrive %0, 64;" ::"r"(10 + w) : "memory");
    TS(10);
    const uint64_t d3 = mkdesc(s23 + 4096, 16, 1024, 1);
#pragma unroll
    for (int c = 0; c < NC; c++) {
        wg_wait<NC - 1>();
        TS(11 + c);
        uint4 pr[2], pi[2];
#pragma unroll
        for (int i = 0; i < 4; i++) {
            const uint32_t er = X[c][0][i], ei = X[c][0][4 + i], orr = X[c][1][i], oi = X[c][1][4 + i];
            const uint32_t ar = KH[c][0][i], ai = KH[c][0][4 + i], br = KH[c][1][i], bi = KH[c][1][4 + i];
            u4r(pr[0], i) = hfms(bi, oi, hfma(br, orr, hfms(ai, ei, hmul(ar, er))));
            u4r(pi[0], i) = hfma(bi, orr, hfma(br, oi, hfma(ai, er, hmul(ar, ei))));
            u4r(pr[1], i) = hfms(ai, oi, hfma(ar, orr, hfms(bi, ei, hmul(br, er))));
            u4r(pi[1], i) = hfma(ai, orr, hfma(ar, oi, hfma(bi, er, hmul(br, ei))));
        }
        if (F_STAG == 3 + c && NC == 2 && wg == 0) asm volatile("bar.arrive %0, 64;" ::"r"(10 + w), "r"(pr[0].x ^ pr[1].w ^ pi[0].y ^ pi[1].z) : "memory");
        wg_fence();
        wgmma_h32_rs<0>(Y[c][0], pr[0], d3, 0);
        wgmma_h32_rs<0>(Y[c][1], pr[1], d3 + 4, 0);
        wgmma_h32_rs<0>(Y[c][0], pi[0], d3 + 2, 1);
        wgmma_h32_rs<0>(Y[c][1], pi[1], d3 + 6, 1);
        wg_commit();
    }
#pragma unroll
    for (int c = 0; c < NC; c++) {
        if (c + 1 < NC) wg_wait<1>(); else wg_wait<0>();
        TS(13 + c);
        uint32_t zr[2][4], zi[2][4];
#pragma unroll
        for (int p = 0; p < 2; p++)
#pragma unroll
            for (int i = 0; i < 4; i++) {
                const uint32_t r = Y[c][p][i], m = Y[c][p][4 + i], tr = u4(tw[p], i), ti = u4(tw[2 + p], i);
                const uint32_t r1 = hfms(tr, m, r), m1 = hfms(ti, r1, m);
                zr[i & 1][2 * p + (i >> 1)] = hfms(tr, m1, r1);
                zi[i & 1][2 * p + (i >> 1)] = m1;
            }
        const int kr = 4 * (mj >> 1) + (mj & 1) + 2 * (mj >> 2), ki = kr ^ 2;
#pragma unroll
        for (int h = 0; h < 2; h++) {
            const uint32_t a = zb + (2 * w + h) * 2048;
            stsm_x4(a + ki * 128 + (((4 * c + mi) ^ (ki & 7)) << 4), zi[h][0], zi[h][1], zi[h][2], zi[h][3]);
            stsm_x4(a + kr * 128 + (((4 * c + mi) ^ (kr & 7)) << 4), zr[h][0], zr[h][1], zr[h][2], zr[h][3]);
        }
    }
    TS(15);
    fence_async_smem();
    TS(16);
    named_bar(1 + wg, 128);
    TS(17);
    float acc[16 * NC];
    const uint64_t dz = mkdesc(zb, 4096, 1024, 1);
    wg_fence();
#pragma unroll
    for (int ks = 0; ks < 4; ks++) wgmma_s4(acc, a4[ks], dz + ks * 256, 0x44EEEE44u, ks > 0);
    wg_commit();
    uint32_t oscale[NC];
#pragma unroll
    for (int c = 0; c < NC; c++) oscale[c] = (lds32(kexp + 4 * c) + 3u) * 0x00800080u;
    bf16* dst = g_x2T[layer] + (size_t)ch0 * XP;
    wg_wait<0>();
    TS(18);
#pragma unroll
    for (int c = 0; c < NC; c++)
#pragma unroll
        for (int p = 0; p < 2; p++) {
            uint32_t r[2][2];
#pragma unroll
            for (int j = 0; j < 2; j++) {
                const float* d = acc + 4 * (4 * c + 2 * p + j);
                const uint32_t y0 = pack2(d[0] + d[2], d[1] + d[3]), y1 = pack2(d[0] - d[2], d[1] - d[3]);
                asm("fma.rn.bf16x2 %0, %1, %2, %3;" : "=r"(r[0][j]) : "r"(y0), "r"(oscale[c]), "r"(j ? x[c][0][p].y : x[c][0][p].x));
                asm("fma.rn.bf16x2 %0, %1, %2, %3;" : "=r"(r[1][j]) : "r"(y1), "r"(oscale[c]), "r"(j ? x[c][1][p].y : x[c][1][p].x));
            }
#pragma unroll
            for (int h = 0; h < 2; h++)
                st_ll((unsigned long long*)(dst + c * XP + 1024 * p + ra[h]), r[h][0] ? r[h][0] : 0x80000000u, r[h][1]);
        }
    TS(19);
}

#define Q_SCHED 3
#define Q_WAITFOR(it) (Q_SCHED == 0 ? (it) - 2 : Q_SCHED == 1 ? ((it) == 3 ? 1 : 0) : Q_SCHED == 2 ? -1 : (it) - 1)
#define Q_S0 8
#define A_HPOS 1
#define A_CSPRE 2
#define R_CONS 192
#define F_PRE 4
#define FIN_DELAY 500
#define T_PF 1
#define K_CSUN 1
constexpr int K_CSU = K_CSUN;
#define G_MAP 1
#define O_TPOS 5
#define O_PASS 3
#define O_DEPTH 4
#define Q_SP 2
#define FIN_SLEEP 0
constexpr int Q_ST = 4;
constexpr int Q_AB = 16384, Q_BB = 30720, Q_SB = Q_AB + Q_BB;
constexpr int Q_EROW = 336;
constexpr int Q_ESLOT = 8 * Q_EROW;
constexpr int Q_EOFF = Q_ST * Q_SB;
constexpr int Q_KG = 2 * Q_SB;
static_assert(3 * Q_ESLOT <= 8192 && Q_KG + KG_TABLES <= Q_EOFF + 4096, "exchange slots, kernel generation");
constexpr int F_EO = Q_EOFF, F_S23 = F_EO + 2 * 8192 + 4096, Q_KDUMP = F_S23 + 8192;
constexpr int Q_SMEM = Q_KDUMP + 6 * KG_RES + TS_SMEM;
__host__ __device__ constexpr int w_grp(int j) { return j < 7 ? 2 * Q_SB + j * 12800 : 20480; }
constexpr int W_RES = 0;

constexpr int Q_ZERO = Q_EOFF + 4096, Q_WOT = Q_EOFF + 8320;

__device__ unsigned g_epoch;
__device__ __align__(1024) unsigned g_bar[4][16][32];
__device__ __align__(1024) uint4 g_wop[8][80][10][8];
__device__ __align__(1024) uint4 g_csp[8][16][96];
__device__ __align__(1024) uint4 g_stp[16][8][64];
__device__ __align__(1024) uint4 g_sp2[16][8][8][8];
__device__ __align__(1024) uint4 g_halo[128][2][5][32];
__device__ __align__(1024) uint4 g_of[8][16][8][5][32];

struct Bars { uint64_t full[Q_ST], empty[Q_ST], wfull[3], ex[7], res, go, prep, ardy, hdone, fdone, idx, att1, pass, staged[2], st[4], kfree; };
constexpr int NBAR = sizeof(Bars) / 8;
__host__ __device__ constexpr int bar_count(int i) {
#define BAR_IS(f) (i == offsetof(Bars, f) / 8)
    return (i >= 4 && i < 8) ? 16 : (BAR_IS(go) || (i >= offsetof(Bars, att1) / 8 && i < offsetof(Bars, st) / 8)) ? 4 : BAR_IS(prep) ? 96 :
           BAR_IS(hdone) ? 6 : BAR_IS(fdone) ? 3 : BAR_IS(kfree) ? 24 : 1;
}
__device__ __forceinline__ void grid_wait(const unsigned* c, int n, unsigned target, int lane) {
    const unsigned* p = c + 32 * min(lane, n - 1);
    unsigned v;
    int spin = 0;
    do { asm volatile("ld.relaxed.gpu.global.u32 %0, [%1];" : "=r"(v) : "l"(p) : "memory"); } while (!__all_sync(~0u, (int)(v - target) >= 0) && ++spin < (1 << 18));
    fence_acquire();
}
__device__ __forceinline__ void grid_arrive(unsigned* c) {
    fence_release();
    asm volatile("red.relaxed.gpu.global.add.u32 [%0], 1;" ::"l"(c) : "memory");
}

#define TMAP(n) ([] { const CUtensorMap* p_; asm volatile("{\n.reg .b64 t;\nmov.b64 t, fused_kernel_param_" #n ";\ncvta.param.u64 %0, t;\n}" : "=l"(p_)); return p_; }())
extern "C" __global__ void __launch_bounds__(384, 1)
fused_kernel(const SsmParams sp, const __grid_constant__ CUtensorMap mX0, const __grid_constant__ CUtensorMap mX1, const __grid_constant__ CUtensorMap mW,
             const __grid_constant__ CUtensorMap mWr,
             const __grid_constant__ CUtensorMap mRes0, const __grid_constant__ CUtensorMap mRes1, const __grid_constant__ CUtensorMap mOut,
             const __grid_constant__ CUtensorMap mWo, const __grid_constant__ CUtensorMap mFin, const __grid_constant__ CUtensorMap mResA) {
    extern __shared__ __align__(1024) char smraw[];
    __shared__ __align__(8) Bars s_bar[2];
    __shared__ __align__(16) float s_cs[240], s_mean[2][64], s_rstd[2][72];
    __shared__ KgShared s_kg;
    __shared__ uint32_t s_epoch;
    const uint32_t sb = s2u(smraw);
    int tid, warp, lane, bx, rank, blk, hg, rot, c0;
    int role;
    {
        const int c = blockIdx.x >> 1, d = c - 41, r = d >= 21 ? 3 : d >= 14 ? 2 : d >= 7 ? 1 : 0;
        const int gp = c < 4 ? 0 : c <= 40 ? (c + 7) & 7 : d - 7 * r + 1;
        const int k = c < 4 ? c : c <= 40 ? (c >> 3) + (gp == 0 ? 3 : gp >= 3 && gp < 7 ? 0 : -1) : (gp >= 3 ? 5 : 4) + r;
        role = G_MAP == 1 ? 16 * k + 2 * gp + (blockIdx.x & 1) : G_MAP == 2 ? 16 * gp + 2 * k + (blockIdx.x & 1) : blockIdx.x;
    }
    auto indices = [&] {
        asm volatile("mov.u32 %0, %%tid.x;" : "=r"(tid));
        asm volatile("mov.u32 %0, %1;" : "=r"(bx) : "r"(role));
        warp = __shfl_sync(~0u, tid >> 5, 0); lane = tid & 31;
        rank = bx & 1; blk = bx & 15; hg = bx >> 4;
        const int u = ((blk >> 1) + hg) & 7;
        rot = (5 * u) >> 2; c0 = 16 * (u & 3);
    };
    indices();
    TS_DECL;
    TS_BEGIN;
#define EPOCH lds32(s2u(&s_epoch))
    int layer = 0;
    uint32_t bars = s2u(s_bar);
#define BAR(f) (bars + (uint32_t)offsetof(Bars, f))
    auto chunk = [&](int it, int s0) {
        const int i = it < s0 ? it : it - 2;
        return (it >> 1) == (s0 >> 1) ? rot + (it & 1) : i < rot ? i : i + 2;
    };
    auto osrc_of = [&](int j) { return j == 0 ? hg : j - 1 < hg ? j - 1 : j; };
    auto issue_w = [&](uint32_t bb, int it, int lay) {
        const int half = rank;
        const int s = it & (Q_ST - 1);
        const uint32_t fb = bb + 8 * s, db = sb + s * Q_SB + Q_AB + half * 15360;
        const int k0 = chunk(it, Q_SP * lay) * 64 + half * 32;
#pragma unroll
        for (int p = 0; p < 3; p++) tma2d_mc(db + p * 4096, TMAP(3), p * DM + hg * 80, k0, fb, 3);
        tma3d_mc(db + 12288, TMAP(4), hg * 80 + 64, k0, 0, fb, 3);
    };
    auto issue_x = [&](int it) {
        const int s = it & (Q_ST - 1), kc = chunk(it, Q_SP * layer);
        mbar_expect(BAR(full) + 8 * s, Q_SB);
        tma3d(sb + s * Q_SB, TMAP(1) + layer, (layer ? blk : kc) * 64, (layer ? kc : blk) * 64, 0, BAR(full) + 8 * s);
    };
    auto clear_fin = [&](uint32_t zero) {
#pragma unroll 1
        for (int i = 0; i < 5; i++) bulk_s2g(g_x2T[1] + (bx * 5 + i) * XP, zero, SEQ * 2);
        bulk_commit();
    };
    {
        KgParams kp;
        kgen_load(kp, bx * 5, warp, lane, sp);
        if (warp < 8) {
            cluster_arrive_relaxed();
        } else {
            const int t2 = tid - 256;
            if (elect_one()) {
                if (warp < 10) { prefetch_tmap(TMAP(3)); prefetch_tmap(TMAP(4)); } else prefetch_tmap(warp == 10 ? TMAP(1) : TMAP(8));
                const uint32_t b0 = bars + (warp >= 10 ? sizeof(Bars) : 0);
                if (warp & 1) {
#pragma unroll
                    for (int i = 0; i < NBAR / 2; i++) mbar_init(b0 + i * 8, bar_count(i));
                } else {
#pragma unroll
                    for (int i = NBAR / 2; i < NBAR; i++) mbar_init(b0 + i * 8, bar_count(i));
                }
                fence_mbar_init();
            }
            __syncwarp();
            cluster_arrive_relaxed();
            TS(29);
            const uint32_t epoch0 = ldg32(&g_epoch);
            sts128(sb + Q_ZERO + t2 * 16, make_uint4(0, 0, 0, 0)); sts128(sb + Q_ZERO + 2048 + t2 * 16, make_uint4(0, 0, 0, 0));
            cluster_wait();
            TS(27);
            if (elect_one()) {
                if (warp < 10) {
                    issue_w(BAR(full), warp - 8, 0);
                } else if (warp == 10) {
                    issue_x(0); issue_x(1);
                    prefetch_l2((const char*)c_fft + bx * (sizeof(c_fft) / 128), sizeof(c_fft) / 128);
                } else {
                    mbar_expect(BAR(idx), 8192 + 6400);
                    asm volatile("cp.async.bulk.tensor.4d.shared::cluster.global.mbarrier::complete_tx::bytes [%0], [%1, {0, 0, %3, %4}], [%2];"
                                 ::"r"(sb + Q_WOT), "l"(TMAP(8)), "r"(BAR(idx)), "r"(10 * hg), "r"(5 * blk) : "memory");
                    bulk_g2s(sb + F_S23, c_fft + 18 * 512, 8192, BAR(idx));
                }
            }
            __syncwarp();
            if (t2 == 0) s_epoch = epoch0;
            TS(30);
        }
        indices();
        kgen_tables(kp, sb + Q_KG, sb + Q_KDUMP, &s_kg, warp, lane TS_PASS);
        if (warp < 8) cluster_wait();
        __syncwarp();
        if (lane == 0) { mbar_arrive_cta(BAR(kfree), 0); mbar_arrive_cta(BAR(kfree), 1); }
        if (warp >= 8) {
            const int t2 = tid - 256;
            float csum[10];
            if (warp == 11 && elect_one()) clear_fin(sb + Q_ZERO);
            __syncwarp();
            if (t2 < 64) stg128(&g_sp2[blk][hg][0][0] + t2, make_uint4(0, 0, 0, 0));
            if (t2 >= 120) stg128((uint4*)g_fs + 8 * bx + t2 - 120, make_uint4(0, 0, 0, 0));
#pragma unroll
            for (int i = 0; i < 3; i++)
                if (t2 + 128 * i < 320) stg128(&g_halo[bx][0][0][0] + t2 + 128 * i, make_uint4(0, 0, 0, 0));
            if (warp == 8) asm volatile("bar.arrive 13, 128;" ::: "memory"); else named_bar(13, 128);
            if (warp > 8) {
                const int hw = warp - 9, mi = lane >> 3, mj = lane & 7;
                mbar_wait(BAR(idx), 0);
                if (hw == 2 && elect_one()) { bulk_s2g(&g_wop[hg][5 * blk], sb + Q_WOT, 6400); bulk_commit(); }
                __syncwarp();
                mbar_wait(BAR(full), 0);
                mbar_wait(BAR(full) + 8, 0);
#pragma unroll
                for (int f = 0; f < 10; f++) csum[f] = 0.f;
#pragma unroll K_CSU
                for (int G = 0; G < 5; G++) {
                    const int row = c0 + 40 * rank + 8 * G + mj;
                    const uint32_t b = sb + (row >> 6) * Q_SB + Q_AB + ((row >> 5) & 1) * 15360;
                    uint32_t r[10];
                    ldsm_x4_t(r[0], r[1], r[2], r[3], b + hw * 4096 + (row & 31) * 128 + ((mi ^ mj) << 4));
                    ldsm_x4_t(r[4], r[5], r[6], r[7], b + hw * 4096 + (row & 31) * 128 + (((4 + mi) ^ mj) << 4));
                    ldsm_x2_t(r[8], r[9], b + 12288 + hw * 1024 + (row & 31) * 32 + (((mi & 1) ^ (mj >> 2)) << 4));
#pragma unroll
                    for (int f = 0; f < 10; f++) csum[f] += bf_lo(r[f]) + bf_hi(r[f]);
                }
                const int q = lane & 3;
                float t[3];
#pragma unroll
                for (int j = 0; j < 3; j++) {
                    float v[4];
#pragma unroll
                    for (int k = 0; k < 4; k++) v[k] = 4 * j + k < 10 ? csum[4 * j + k] : 0.f;
                    const float a0 = ((q & 2) ? v[2] : v[0]) + __shfl_xor_sync(~0u, (q & 2) ? v[0] : v[2], 2);
                    const float a1 = ((q & 2) ? v[3] : v[1]) + __shfl_xor_sync(~0u, (q & 2) ? v[1] : v[3], 2);
                    t[j] = ((q & 1) ? a1 : a0) + __shfl_xor_sync(~0u, (q & 1) ? a0 : a1, 1);
                }
                st_ll4(&g_csp[hg][blk][tid - 288], ~EPOCH & 1u, __float_as_uint(t[0]), __float_as_uint(t[1]), __float_as_uint(t[2]));
            }
        }
        TS(1);
    }

    uint4 fa1[4], ftw[4];
    auto conv_tables = [&] {
#pragma unroll
        for (int i = 0; i < 4; i++) { fa1[i] = ldg_tab(i, tid & 127); ftw[i] = ldg_tab(8 + i, tid & 127); }
    };
    auto conv_done = [&] {
        if (layer == 0) {
            named_bar(1 + (warp >> 2), 128);
            if ((tid & 127) == 0) {
                mbar_arrive(BAR(fdone));
                grid_arrive(g_bar[2][hg]);
            }
            __syncwarp();
        }
        TS(20);
    };
    if (warp >= 8) {
    asm volatile("setmaxnreg.dec.sync.aligned.u32 %0;" ::"n"(504 - 2 * R_CONS));
#pragma unroll 1
    for (; layer < 2; layer++, bars += sizeof(Bars)) {
        indices();
        TS_PHASE(2 * layer);
        if (warp == 8) {
            if (layer) {
                grid_wait(g_bar[2][0], 8, 48 * (EPOCH + 1), lane);
                mbar_wait(BAR(fdone) - sizeof(Bars), 0);
                fence_async_global();
                TS(1);
            }
            if (elect_one()) {
#pragma unroll 1
                for (int it = layer ? 0 : 2; it < 10; it++) {
                    if (it >= Q_ST) mbar_wait(BAR(empty) + 8 * (it & (Q_ST - 1)), ((it >> 2) - 1) & 1);
                    else if (layer == 0) mbar_wait(BAR(kfree), 0);
                    else if (it > 0 && Q_WAITFOR(it) >= 0) mbar_wait(BAR(full) + 8 * Q_WAITFOR(it), 0);
                    if (it == Q_ST + Q_SP * layer) mbar_wait(BAR(hdone), 0);
                    issue_x(it);
                    if (layer == 0 || it >= F_PRE) issue_w(BAR(full), it, layer);
                }
                if (T_PF) { prefetch_tmap(TMAP(5) + layer); prefetch_tmap(TMAP(7)); prefetch_tmap(TMAP(10)); }
                if (layer == 0) { mbar_wait(BAR(prep), 0); fence_async_global(); }
#pragma unroll 1
                for (int j = 0; j < 8; j++) {
                    const int b = (j + 1) >> 2;
                    const uint32_t fb = BAR(wfull) + 8 * b;
                    if (j == 0 || j == 3 || j == 7) {
                        mbar_wait(BAR(empty) + 8 * ((2 + b) & 3), b < 2);
                        TS(11 + b);
                        mbar_expect(fb, (b == 0 ? 3 : b == 1 ? 4 : 1) * 12800);
                    }
                    bulk_g2s_mc(sb + w_grp(j) + rank * 6400, &g_wop[hg][osrc_of(j) * 10 + rank * 5], 6400, fb, 3);
                }
                mbar_expect(BAR(res), 20480);
                if (layer) {
                    tma3d(sb + W_RES, TMAP(6), blk * 64, hg * 80, 0, BAR(res));
                } else {
#pragma unroll 1
                    for (int p = 0; p < 2; p++) {
                        tma3d(sb + W_RES + p * 10240, TMAP(10), hg * 80, blk * 64, p, BAR(res));
                        tma3d(sb + W_RES + p * 10240 + 8192, TMAP(5), hg * 80 + 64, blk * 64, p, BAR(res));
                    }
                }
            }
            __syncwarp();
        } else {
            const int ht = tid - 288, hw = warp - 9, mi = lane >> 3, mj = lane & 7, g = lane >> 2, q = lane & 3;
            auto F = [](uint32_t x) { return __uint_as_float(x); };
            auto U = [](float x) { return __float_as_uint(x); };
            const uint32_t lb = layer ^ 1, eb = ~EPOCH & 1u;
            mbar_wait(BAR(full) + 8 * Q_SP * layer, 0);
            mbar_wait(BAR(full) + 8 * Q_SP * layer + 8, 0);
            if (ht == 0) TSX(2, 2);
            uint32_t xf[3][20];
#pragma unroll
            for (int i = 0; i < 3; i++) {
                const int tile = min(hw + 3 * i, 7);
#pragma unroll
                for (int k = 0; k < 5; k++) {
                    const int ch = c0 + 16 * k + 8 * (mi >> 1), tok = 16 * (tile & 3) + 8 * (mi & 1);
                    const uint32_t a = sb + ((ch >> 6) + Q_SP * layer) * Q_SB + (tile >> 2) * 8192;
                    if (layer == 0) ldsm_x4(xf[i][4 * k], xf[i][4 * k + 1], xf[i][4 * k + 2], xf[i][4 * k + 3], a + (tok + mj) * 128 + ((((ch & 63) >> 3) ^ mj) << 4));
                    else ldsm_x4_t(xf[i][4 * k], xf[i][4 * k + 1], xf[i][4 * k + 2], xf[i][4 * k + 3], a + ((ch & 63) + mj) * 128 + (((tok >> 3) ^ mj) << 4));
                }
            }
            fence_async_smem();
            __syncwarp();
            if (lane == 0) { mbar_arrive_cta(BAR(hdone), 0); mbar_arrive_cta(BAR(hdone), 1); }
            if (ht == 0) TSX(2, 3);
            if (layer == 0) {
                if (hw == 2 && elect_one()) { bulk_wait(); fence_async_global(); grid_arrive(g_bar[3][hg]); }
                __syncwarp();
                mbar_wait(BAR(kfree), 0);
            }
            if (ht == 0) TSX(2, 8);
#pragma unroll 1
            for (int tile = hw; tile < 8; tile += 3) {
                float a[4] = {0.f, 0.f, 0.f, 0.f};
#pragma unroll
                for (int j = 0; j < 20; j++) {
                    const float lo = bf_lo(xf[0][j]), hi = bf_hi(xf[0][j]);
                    a[2 * (j & 1)] += lo + hi; a[2 * (j & 1) + 1] = fmaf(lo, lo, fmaf(hi, hi, a[2 * (j & 1) + 1]));
                    xf[0][j] = xf[1][j]; xf[1][j] = xf[2][j];
                }
#pragma unroll
                for (int j = 0; j < 4; j++) { a[j] += __shfl_xor_sync(~0u, a[j], 1); a[j] += __shfl_xor_sync(~0u, a[j], 2); }
                if (q == 0) st_ll4(&g_stp[blk][hg][8 * tile + g], (U(a[0]) & ~1u) | lb, U(a[1]), U(a[2]), U(a[3]));
            }
            if (ht == 0) TSX(2, 4);
            if (layer == 0) {
                float t[4] = {0.f, 0.f, 0.f, 0.f};
                uint4 v[16];
                int spin = 0;
                uint32_t bad;
                do {
                    bad = 0;
#pragma unroll
                    for (int j = 0; j < 16; j++) v[j] = ld_ll4(&g_csp[hg][j][ht]);
#pragma unroll
                    for (int j = 0; j < 16; j++) bad |= v[j].x ^ eb;
                } while ((bad & 1u) && ++spin < (1 << 18));
#pragma unroll
                for (int j = 0; j < 16; j++) { t[0] += F(v[j].y); t[1] += F(v[j].z); t[2] += F(v[j].w); }
#pragma unroll
                for (int j = 0; j < 3; j++) if (q + 4 * j < 10) s_cs[80 * hw + 20 * (g >> 1) + 2 * (q + 4 * j) + (g & 1)] = t[j];
                if (hw == 2) grid_wait(g_bar[3][0], 8, 16 * (EPOCH + 1), lane);
            }
            if (ht == 0) TSX(2, 15);
            if (ht < 80) {
                const bool halo = ht >= 64;
                const int p = halo ? (ht >> 3) & 1 : ht >> 5, i = halo ? (ht & 7) - 8 : 8 + 2 * (ht & 24) + (ht & 7);
                const uint4* src = &g_stp[halo && blk ? blk - 1 : blk][0][halo ? 32 * p + 24 + (ht & 7) : ht];
                uint4 v[8];
                int spin = 0;
                uint32_t bad;
                do {
                    bad = 0;
#pragma unroll
                    for (int j = 0; j < 8; j++) v[j] = ld_ll4(src + 64 * j);
#pragma unroll
                    for (int j = 0; j < 8; j++) bad |= v[j].x ^ lb;
                } while ((bad & 1u) && ++spin < (1 << 18));
                float t[4] = {0.f, 0.f, 0.f, 0.f};
#pragma unroll
                for (int j = 0; j < 8; j++) { t[0] += F(v[j].x); t[1] += F(v[j].y); t[2] += F(v[j].z); t[3] += F(v[j].w); }
                const uint32_t s0 = ln_finish_packed(t[0], t[1]), s1 = ln_finish_packed(t[2], t[3]);
                if (!halo) { s_mean[p][i - 8] = bf_hi(s0); s_mean[p][i] = bf_hi(s1); s_rstd[p][i] = frcp(bf_lo(s0)); }
                s_rstd[p][i + 8] = frcp(bf_lo(s1));
            }
            fence_acquire();
            mbar_arrive(BAR(prep));
            if (ht == 0) TSX(2, 5);
        }
        __syncwarp();
        TS_PHASE(2 * layer + 1);
        TS(0);
        indices();
        {
            const uint4 ko[2] = {ldg_tab(16, tid & 127), ldg_tab(17, tid & 127)};
            conv_tables();
            mbar_wait(BAR(att1), 0);
            kernel_stage<1>(ko, sb + Q_KDUMP + 4 * KG_RES, sb + F_EO + 2 * 8192, warp & 3, lane);
            fence_async_smem();
            named_bar(3, 128);
        }
        conv_wg<1>(5 * bx + 4, layer, sb + F_EO + 2 * 8192, sb + 2 * Q_SB, sb + F_S23, s2u(&s_kg.kexp[4]), sb + 3 * Q_SB, BAR(st), warp, lane, fa1, ftw,
        [&] {
            if (warp >= 10) {
                const int i = warp - 10;
                mbar_wait(BAR(staged) + 8 * i, 0);
                if (elect_one()) {
                    asm volatile("cp.async.bulk.tensor.2d.global.shared::cta.bulk_group [%0, {%2, %3}], [%1];"
                                 ::"l"(TMAP(7)), "r"(sb + W_RES + i * 10240), "r"(1024 * i + 64 * blk), "r"(hg * 80) : "memory");
                    bulk_commit();
                    bulk_wait();
                    fence_async_global();
                    grid_arrive(g_bar[layer][hg]);
                }
                __syncwarp();
            } else if (warp == 9) {
                auto F = [](uint32_t x) { return __uint_as_float(x); };
                mbar_wait(BAR(staged) + 8 * (hg >> 2), 0);
                const uint4* src = &g_sp2[blk][hg][0][0] + lane;
                uint4 a, b;
                int spin = 0;
                do { a = ld_ll4(src); b = ld_ll4(src + 32); } while (__any_sync(~0u, ~((a.x ^ layer) & (b.x ^ layer)) & 1u) && ++spin < (1 << 18));
                const bool up = lane & 8;
                const float s0 = F(a.x) + F(b.x), q0 = F(a.y) + F(b.y), s1 = F(a.z) + F(b.z), q1 = F(a.w) + F(b.w);
                float sm = (up ? s1 : s0) + __shfl_xor_sync(~0u, up ? s0 : s1, 8), sq = (up ? q1 : q0) + __shfl_xor_sync(~0u, up ? q0 : q1, 8);
                sm += __shfl_xor_sync(~0u, sm, 16); sq += __shfl_xor_sync(~0u, sq, 16);
                const float m = sm * (1.0f / DM), r = frsq(fmaxf(fmaf(sq, 1.0f / DM, fmaf(-m, m, 1e-5f)), 1e-5f));
                const uint32_t v = __float_as_uint(lane & 16 ? -m * r : r);
                const uint32_t v0 = __shfl_sync(~0u, v, 4 * lane), v1 = __shfl_sync(~0u, v, 4 * lane + 1), v2 = __shfl_sync(~0u, v, 4 * lane + 2), v3 = __shfl_sync(~0u, v, 4 * lane + 3);
                if (lane < 8) st_ll4((uint4*)(g_fs[lane >> 2] + 1024 * (hg >> 2) + 64 * blk + 16 * (hg & 3)) + (lane & 3), (v0 & ~1u) | (layer ^ 1), v1, v2, v3);
            }
            named_bar(3, 128);
        }, [&] { mbar_wait(BAR(ardy), 0); }, [&] {
            if (T_PF && tid == 352) prefetch_tmap(layer ? TMAP(9) : TMAP(2));
            if (layer == 0 && warp - 8 < F_PRE && elect_one()) issue_w(BAR(full) + sizeof(Bars), warp - 8, 1);
            __syncwarp();
        } TS_PASS);
        conv_done();
    }
    } else {
#pragma unroll 1
    for (; layer < 2; layer++, bars += sizeof(Bars)) {
    indices();
    TS_PHASE(2 * layer);
    const int wg = warp >> 2, w = warp & 3;
    const int mi = lane >> 3, mj = lane & 7, g = lane >> 2, q = lane & 3;
    TS(2);
    float acc[120];
#pragma unroll
    for (int i = 0; i < 120; i++) acc[i] = 0.f;
    auto release = [&](int it) {
        if (lane == 0) { mbar_arrive_cta(BAR(empty) + 8 * (it & (Q_ST - 1)), 0); mbar_arrive_cta(BAR(empty) + 8 * (it & (Q_ST - 1)), 1); }
    };
#pragma unroll 1
    for (int it = 0; it < 10; it++) {
        const int s = it & (Q_ST - 1);
        const uint32_t st = sb + s * Q_SB;
        const bool hold = wg == 1 && it == Q_S0;
        if (hold) {
            wg_wait<0>();
            release(it - 1);
            mbar_wait(BAR(go), 0);
        }
        mbar_wait(BAR(full) + 8 * (s), (it >> 2) & 1);
        if (it < 2) TS(3 + it);
        if (it == 6) TS(5);
        if (it == 9) TS(6);
        const uint64_t da = mkdesc(st + wg * 8192, 16, 1024, 1);
        const uint64_t db = mkdesc(st + Q_AB, 4096, 1024, 1);
        const uint64_t dr = mkdesc(st + Q_AB + 12288, 1024, 256, 3);
        if (layer == 0) {
            wg_fence();
#pragma unroll
            for (int ks = 0; ks < 4; ks++) {
                const int sc = 1;
                wgmma_n192<0, 1>(*(float(*)[96]) & acc[0], da + ks * 2, db + (ks >> 1) * 960 + (ks & 1) * 128, sc);
                wgmma_n48<0, 1>(*(float(*)[24]) & acc[96], da + ks * 2, dr + (ks >> 1) * 960 + (ks & 1) * 32, sc);
            }
            wg_commit();
        } else {
            wg_fence();
#pragma unroll
            for (int ks = 0; ks < 4; ks++) {
                const int sc = 1;
                wgmma_n192<1, 1>(*(float(*)[96]) & acc[0], da + ks * 128, db + (ks >> 1) * 960 + (ks & 1) * 128, sc);
                wgmma_n48<1, 1>(*(float(*)[24]) & acc[96], da + ks * 128, dr + (ks >> 1) * 960 + (ks & 1) * 32, sc);
            }
            wg_commit();
        }
        wg_wait<1>();
        if (it > 0 && !hold) release(it - 1);
    }
    if (wg == 0 && lane == 0) mbar_arrive(BAR(go));
    asm volatile("setmaxnreg.inc.sync.aligned.u32 %0;" ::"n"(R_CONS));
    mbar_wait(BAR(prep), 0);
    const uint32_t ob = layer ^ 1;
    const bool first = (blk == 0 && w == 0);
    const bool sel0 = (2 * q > g), sel1 = (2 * q + 1 > g);
    constexpr float SC = 0.22360679774997896f * 1.4426950408889634f;
    const float m0 = s_mean[wg][16 * w + g], m1 = s_mean[wg][8 + 16 * w + g];
    uint4 cs[3][5];
    auto cs_load = [&](int p) {
#pragma unroll
        for (int i = 0; i < 5; i++) cs[p][i] = lds128(s2u(&s_cs[80 * p + 20 * q + 4 * i]));
    };
    if (A_CSPRE >= 1) cs_load(1);
    if (A_CSPRE >= 2) cs_load(2);
    wg_wait<0>();
    if (A_CSPRE < 1) cs_load(1);
    if (A_CSPRE < 2) cs_load(2);
    TS(7);
    uint32_t ql[10], qh[10], kl[10], kh[10], vl[10], vh[10];
    auto fold = [&](int p, int f, int h) {
        const int j = (f < 8) ? 8 * p + f : 24 + 2 * p + (f - 8);
        const float c0 = __uint_as_float(u4(cs[p][f >> 1], 2 * (f & 1))), c1 = __uint_as_float(u4(cs[p][f >> 1], 2 * (f & 1) + 1));
        const float m = h ? m1 : m0;
        return pack2(fmaf(-m, c0, acc[4 * j + 2 * h]), fmaf(-m, c1, acc[4 * j + 2 * h + 1]));
    };
#pragma unroll
    for (int f = 0; f < 10; f++) { kh[f] = fold(1, f, 1); vh[f] = fold(2, f, 1); }
    {
        const uint32_t mk = w == 3 ? 1u : 0u;
        auto mark = [&](uint32_t& v) { v = (v & ~mk) | (ob & mk); };
        mark(kh[0]); mark(kh[5]); mark(vh[0]); mark(vh[4]); mark(vh[8]);
    }
    if (w == 3) {
        uint4* hp = &g_halo[bx][wg][0][lane];
        st_ll4(hp, kh[0], kh[1], kh[3], kh[4]); st_ll4(hp + 32, kh[5], kh[6], kh[8], kh[9]);
        st_ll4(hp + 64, vh[0], vh[1], vh[2], vh[3]); st_ll4(hp + 96, vh[4], vh[5], vh[6], vh[7]);
        st_ll4(hp + 128, vh[8], vh[9], kh[2], kh[7]);
    } else {
        const uint32_t a = sb + Q_EOFF + wg * 8192 + w * Q_ESLOT + mj * Q_EROW + mi * 16;
        stsm_x4(a, kh[0], kh[1], kh[3], kh[4]);
        stsm_x4(a + 64, kh[5], kh[6], kh[8], kh[9]);
        stsm_x4(a + 128, vh[0], vh[1], vh[2], vh[3]);
        stsm_x4(a + 192, vh[4], vh[5], vh[6], vh[7]);
        stsm_x4(a + 256, vh[8], vh[9], kh[2], kh[7]);
        __syncwarp();
        if (lane == 0) mbar_arrive(BAR(ex) + 8 * warp);
    }
    TS(9);
    cs_load(0);
#pragma unroll
    for (int f = 0; f < 10; f++) { kl[f] = fold(1, f, 0); vl[f] = fold(2, f, 0); }
#pragma unroll
    for (int f = 0; f < 10; f++) { ql[f] = fold(0, f, 0); qh[f] = fold(0, f, 1); }
    auto rs = [&](int i) { return __uint_as_float(lds32(s2u(&s_rstd[wg][16 * w + i]))); };
    const float kx0 = rs(2 * q + (sel0 ? 0 : 8)), kx1 = rs(2 * q + (sel1 ? 1 : 9)), ky0 = rs(2 * q + (sel0 ? 8 : 16)), ky1 = rs(2 * q + (sel1 ? 9 : 17));
    const float rx = SC * rs(8 + g), ry = SC * rs(16 + g), cx0 = rx * kx0, cx1 = rx * kx1, cy0 = ry * ky0, cy1 = ry * ky1;
    uint4 hv[5];
    const uint4* hp = &g_halo[bx - 1][wg][0][lane];
    auto prev = [&] {
        if (w > 0) {
            const uint32_t a = sb + Q_EOFF + wg * 8192 + (w - 1) * Q_ESLOT + mj * Q_EROW + mi * 16;
            mbar_wait(BAR(ex) + 8 * (warp - 1), 0);
            ldsm_x4(hv[0].x, hv[0].y, hv[0].z, hv[0].w, a);
            ldsm_x4(hv[1].x, hv[1].y, hv[1].z, hv[1].w, a + 64);
            ldsm_x4_t(hv[2].x, hv[2].y, hv[2].z, hv[2].w, a + 128);
            ldsm_x4_t(hv[3].x, hv[3].y, hv[3].z, hv[3].w, a + 192);
            ldsm_x2_t(hv[4].x, hv[4].y, a + 256);
            ldsm_x2(hv[4].z, hv[4].w, a + 288 - (lane >> 4) * 32);
        } else if (blk > 0) {
#pragma unroll
            for (int f = 0; f < 5; f++) hv[f] = ld_ll4(hp + 32 * f);
        } else {
#pragma unroll
            for (int f = 0; f < 5; f++) hv[f] = make_uint4(0, 0, 0, 0);
        }
    };
    if (A_HPOS == 0) prev();
    uint32_t vt[10][2];
#pragma unroll
    for (int f = 0; f < 10; f++) { vt[f][0] = movm_t(vl[f]); vt[f][1] = movm_t(vh[f]); }
    if (A_HPOS == 1) prev();
    TS(10);
    auto FA = [](int h) { return h == 0 ? 0 : h == 1 ? 3 : h == 2 ? 5 : 8; };
    auto FH = [](int h) { return h < 2 ? 2 : 7; };
    const uint32_t pm = (sel0 ? 0xFFFFu : 0u) | (sel1 ? 0xFFFF0000u : 0u);
    auto softmax = [&](float x0, float x1, float k0, float k1) {
        float mx = fmaxf(x0, x1);
        mx = fmaxf(mx, __shfl_xor_sync(~0u, mx, 1));
        mx = fmaxf(mx, __shfl_xor_sync(~0u, mx, 2));
        x0 = ex2(x0 - mx); x1 = ex2(x1 - mx);
        float sx = x0 + x1;
        sx += __shfl_xor_sync(~0u, sx, 1);
        sx += __shfl_xor_sync(~0u, sx, 2);
        const float ix = frcp(sx);
        return pack2(x0 * k0 * ix, x1 * k1 * ix);
    };
    uint32_t qm[4][2], py[4];
    float sl[4][2];
#pragma unroll
    for (int h = 0; h < 4; h++) {
        const int fa = FA(h), fb = fa + 1, fh = FH(h);
        const bool mine = (h & 1) ? (q >= 2) : (q < 2);
        qm[h][0] = mine ? ql[fh] : 0u; qm[h][1] = mine ? qh[fh] : 0u;
        float S1[4] = {0.f, 0.f, 0.f, 0.f}, S2[4] = {0.f, 0.f, 0.f, 0.f};
        mma16816(S1, ql[fa], qh[fa], ql[fb], qh[fb], kl[fa], kl[fb]); mma1688(S1, qm[h][0], qm[h][1], kl[fh]);
        mma16816(S2, ql[fa], qh[fa], ql[fb], qh[fb], kh[fa], kh[fb]); mma1688(S2, qm[h][0], qm[h][1], kh[fh]);
        sl[h][0] = S1[0]; sl[h][1] = S1[1];
        py[h] = softmax((sel0 ? S1[2] : S2[2]) * cy0, (sel1 ? S1[3] : S2[3]) * cy1, ky0, ky1);
    }
    TS(11);
    if (w == 0 && blk > 0) {
        int spin = 0;
        while (__any_sync(~0u, ((hv[0].x ^ ob) | (hv[1].x ^ ob) | (hv[2].x ^ ob) | (hv[3].x ^ ob) | (hv[4].x ^ ob)) & 1u) && ++spin < (1 << 18)) {
#pragma unroll
            for (int f = 0; f < 5; f++) hv[f] = ld_ll4(hp + 32 * f);
        }
#pragma unroll
        for (int f = 2; f < 4; f++) hv[f] = make_uint4(movm_t(hv[f].x), movm_t(hv[f].y), movm_t(hv[f].z), movm_t(hv[f].w));
        hv[4].x = movm_t(hv[4].x); hv[4].y = movm_t(hv[4].y);
    }
    const uint32_t kp[10] = {hv[0].x, hv[0].y, hv[4].z, hv[0].z, hv[0].w, hv[1].x, hv[1].y, hv[4].w, hv[1].z, hv[1].w};
    const uint32_t vp[10] = {hv[2].x, hv[2].y, hv[2].z, hv[2].w, hv[3].x, hv[3].y, hv[3].z, hv[3].w, hv[4].x, hv[4].y};
    TS(12);
    const uint4 ko[2] = {ldg_tab(16, tid & 127), ldg_tab(17, tid & 127)};
    const float bx0 = first && sel0 ? -INFINITY : 0.f, bx1 = first && sel1 ? -INFINITY : 0.f;
    float oacc[10][4];
#pragma unroll
    for (int h = 0; h < 4; h++) {
        const int fa = FA(h), fb = fa + 1, fh = FH(h);
        const bool mine = (h & 1) ? (q >= 2) : (q < 2);
        float S0[4] = {0.f, 0.f, 0.f, 0.f};
        mma16816(S0, ql[fa], qh[fa], ql[fb], qh[fb], kp[fa], kp[fb]); mma1688(S0, qm[h][0], qm[h][1], kp[fh]);
        const uint32_t px = softmax(fmaf(sel0 ? S0[0] : sl[h][0], cx0, bx0), fmaf(sel1 ? S0[1] : sl[h][1], cx1, bx1), kx0, kx1);
#pragma unroll
        for (int i = 0; i < 3; i++) {
            const int f = (i == 0) ? fa : (i == 1) ? fb : fh;
            float O[4] = {0.f, 0.f, 0.f, 0.f};
            mma16816(O, px & ~pm, py[h] & pm, 0u, py[h] & ~pm, vt[f][0], vt[f][1]);
            mma1688(O, px & pm, 0u, vp[f]);
            if (i < 2 || !(h & 1) || mine) { oacc[f][0] = O[0]; oacc[f][1] = O[1]; oacc[f][2] = O[2]; oacc[f][3] = O[3]; }
        }
    }
    TS(13);
    constexpr int ON = O_DEPTH + 2;
    uint4 of[ON][5];
    {
        uint4* dst = &g_of[hg][blk][warp][0][lane];
#pragma unroll
        for (int k = 0; k < 5; k++) {
            of[0][k] = make_uint4((pack2(oacc[2 * k][0], oacc[2 * k][1]) & ~1u) | ob, pack2(oacc[2 * k][2], oacc[2 * k][3]),
                                  pack2(oacc[2 * k + 1][0], oacc[2 * k + 1][1]), pack2(oacc[2 * k + 1][2], oacc[2 * k + 1][3]));
            st_ll4(dst + 32 * k, of[0][k].x, of[0][k].y, of[0][k].z, of[0][k].w);
        }
    }
    if (wg == 1 && lane == 0) mbar_arrive(BAR(att1));
    TS(14);
    float aw[40];
    auto omma = [&](int j) {
        const uint64_t dm = mkdesc(sb + w_grp(j), 1280, 128, 0);
        wg_fence();
#pragma unroll
        for (int k = 0; k < 5; k++) wgmma_rs80(aw, of[j % ON][k], dm + k * 160, j + k > 0);
        wg_commit();
    };
    mbar_wait(BAR(wfull), 0);
    omma(0);
    named_bar(1 + wg, 128);
    kernel_stage<2>(ko, sb + Q_KDUMP + 2 * wg * KG_RES, sb + F_EO + wg * 8192, w, lane);
    TS(8);
    const uint4* osrc = &g_of[0][blk][warp][0][lane];
    auto oload = [&](int j) {
        const uint4* p = osrc + osrc_of(j) * 20480;
#pragma unroll
        for (int k = 0; k < 5; k++) of[j % ON][k] = ld_ll4(p + 32 * k);
    };
    {
        const uint32_t* pp = &g_of[osrc_of(1 + min(lane, 6))][blk][warp][4][31].x;
        uint32_t v;
        int spin = 0;
        do { asm volatile("ld.relaxed.gpu.global.u32 %0, [%1];" : "=r"(v) : "l"(pp) : "memory"); } while (__any_sync(~0u, (v & 1u) != ob) && ++spin < (1 << 18));
    }
    TS(15);
    if (O_PASS && wg == 1) mbar_wait(BAR(pass), 0);
#pragma unroll
    for (int j = 1; j <= O_DEPTH; j++) oload(j);
    TS(16);
#pragma unroll
    for (int j = 1; j < 8; j++) {
        if (j == 3 || j == 7) mbar_wait(BAR(wfull) + 8 * ((j + 1) >> 2), 0);
        const uint4* f = of[j % ON];
        int spin = 0;
        while (__any_sync(~0u, ((f[0].x ^ ob) | (f[1].x ^ ob) | (f[2].x ^ ob) | (f[3].x ^ ob) | (f[4].x ^ ob)) & 1u) && ++spin < (1 << 18)) oload(j);
        if (j + O_DEPTH < 8) { wg_wait<1>(); oload(j + O_DEPTH); }
        if (j == O_PASS && wg == 0 && lane == 0) mbar_arrive(BAR(pass));
        if (j == O_TPOS) { wg_wait<1>(); conv_tables(); }
        if (j == 1) TS(17);
        if (j == 5) TS(18);
        omma(j);
    }
    wg_wait<2>();
    uint32_t res[20];
    mbar_wait(BAR(res), 0);
    const uint32_t ta = (8 * (mi >> 1) + mj) * 128 + (((2 * w + (mi & 1)) ^ mj) << 4);
    if (layer == 0) {
        const int tok = 16 * w + 8 * (mi & 1) + mj;
#pragma unroll
        for (int k = 0; k < 4; k++)
            ldsm_x4(res[4 * k], res[4 * k + 1], res[4 * k + 2], res[4 * k + 3], sb + W_RES + wg * 10240 + tok * 128 + (((2 * k + (mi >> 1)) ^ mj) << 4));
        ldsm_x4(res[16], res[17], res[18], res[19], sb + W_RES + wg * 10240 + 8192 + tok * 32 + (((mi >> 1) ^ (mj >> 2)) << 4));
    } else {
#pragma unroll
        for (int k = 0; k < 5; k++) ldsm_x4_t(res[4 * k], res[4 * k + 1], res[4 * k + 2], res[4 * k + 3], sb + W_RES + wg * 10240 + k * 2048 + ta);
    }
    named_bar(1 + wg, 128);
    wg_wait<0>();
    TS(19);
#pragma unroll
    for (int i = 0; i < 20; i++) {
        const uint32_t y = pack2(aw[2 * i], aw[2 * i + 1]);
        asm("add.rn.bf16x2 %0, %0, %1;" : "+r"(res[i]) : "r"(y));
    }
#pragma unroll
    for (int k = 0; k < 5; k++) stsm_x4_t(sb + W_RES + wg * 10240 + k * 2048 + ta, res[4 * k], res[4 * k + 1], res[4 * k + 2], res[4 * k + 3]);
    fence_async_smem();
    __syncwarp();
    if (lane == 0) mbar_arrive(BAR(staged) + 8 * wg);
    TS(20);
    {
        float sm[4] = {0.f, 0.f, 0.f, 0.f}, d0[4] = {0.f, 0.f, 0.f, 0.f}, d1[4] = {0.f, 0.f, 0.f, 0.f};
#pragma unroll
        for (int k = 0; k < 5; k++) {
            mma16816(sm, res[4 * k], res[4 * k + 1], res[4 * k + 2], res[4 * k + 3], 0x3F803F80u, 0x3F803F80u);
            mma16816(d0, res[4 * k], res[4 * k + 1], res[4 * k + 2], res[4 * k + 3], res[4 * k], res[4 * k + 2]);
            mma16816(d1, res[4 * k], res[4 * k + 1], res[4 * k + 2], res[4 * k + 3], res[4 * k + 1], res[4 * k + 3]);
        }
        if (q == (g >> 1))
            st_ll4(&g_sp2[blk][warp][hg][g], (__float_as_uint(sm[0]) & ~1u) | ob, __float_as_uint((g & 1) ? d0[1] : d0[0]), __float_as_uint(sm[2]),
                   __float_as_uint((g & 1) ? d1[3] : d1[2]));
    }
    if (O_TPOS == 9) conv_tables();
    TS(21);
    named_bar(1 + wg, 128);
    TS(22);
    TS_PHASE(2 * layer + 1);
    TS(0);
    indices();
    conv_wg<2>(5 * bx + 2 * (warp >> 2), layer, sb + F_EO + (warp >> 2) * 8192, sb + (warp >> 2) * Q_SB, sb + F_S23, s2u(&s_kg.kexp[2 * (warp >> 2)]),
               sb + 3 * Q_SB, BAR(st), warp, lane, fa1, ftw, [] {}, [&] {
        if (warp == 0) {
            grid_wait(g_bar[layer][0], 8, 32 * (EPOCH + 1), lane);
            if (lane == 0) mbar_arrive(BAR(ardy));
        } else {
            mbar_wait(BAR(ardy), 0);
        }
    }, [] {} TS_PASS);
    conv_done();
    asm volatile("setmaxnreg.dec.sync.aligned.u32 168;");
    }
    named_bar(1 + (warp >> 2), 128);
    asm volatile("setmaxnreg.dec.sync.aligned.u32 %0;" ::"n"(504 - 2 * R_CONS));
    }
    indices();
    __syncthreads();
    if (FIN_DELAY) { const long long t0 = clock64(); while (clock64() - t0 < FIN_DELAY) {} }
    if (tid < 320) {
        const int p = warp & 1, cq = 4 * (warp >> 1) + (lane >> 3), tg = lane & 7;
        const uint4* src = (const uint4*)(g_x2T[1] + (size_t)(80 * hg + 4 * cq) * XP + 1024 * p + 64 * blk + 8 * tg);
        uint4 v[4];
#pragma unroll
        for (int i = 0; i < 4; i++) v[i] = make_uint4(0, 0, 0, 0);
        int spin = 0;
        while (true) {
            bool ok = true;
#pragma unroll
            for (int i = 0; i < 4; i++) if (v[i].x == 0u || v[i].z == 0u) v[i] = ld_ll4(src + i * (XP / 8));
#pragma unroll
            for (int i = 0; i < 4; i++) ok = ok && v[i].x != 0u && v[i].z != 0u;
            if (ok || ++spin >= (1 << 18)) break;
            if (FIN_SLEEP) __nanosleep(FIN_SLEEP);
        }
        TS(21);
#pragma unroll
        for (int i = 0; i < 8; i++) {
            const uint32_t sel = (i & 1) ? 0x7632 : 0x5410;
            asm volatile("st.shared.v2.u32 [%0], {%1, %2};" ::"r"(sb + (8 * (2 * i + p) + tg) * 160 + cq * 8),
                         "r"(__byte_perm(u4(v[0], i >> 1), u4(v[1], i >> 1), sel)), "r"(__byte_perm(u4(v[2], i >> 1), u4(v[3], i >> 1), sel)) : "memory");
        }
        fence_async_smem();
    }
    __syncthreads();
    if (warp == 0 && elect_one()) {
        asm volatile("cp.async.bulk.tensor.3d.global.shared::cta.bulk_group [%0, {%2, %3, 0}], [%1];" ::"l"(TMAP(9)), "r"(sb), "r"(80 * hg), "r"(8 * blk) : "memory");
        bulk_commit();
        asm volatile("cp.async.bulk.wait_group.read 0;" ::: "memory");
    }
    if (bx == 0 && tid == 0) g_epoch = EPOCH + 1;
    TS(22);
    TS_END;
}
typedef CUresult (*EncodeTiledFn)(CUtensorMap*, CUtensorMapDataType, cuuint32_t, void*, const cuuint64_t*, const cuuint64_t*, const cuuint32_t*,
                                  const cuuint32_t*, CUtensorMapInterleave, CUtensorMapSwizzle, CUtensorMapL2promotion, CUtensorMapFloatOOBfill);

static void make_map(EncodeTiledFn enc, CUtensorMap* m, const void* base, int rank, const cuuint64_t* dims, const cuuint64_t* strides,
                     const cuuint32_t* box, CUtensorMapSwizzle sw) {
    cuuint32_t es[4] = {1, 1, 1, 1};
    enc(m, CU_TENSOR_MAP_DATA_TYPE_BFLOAT16, rank, (void*)base, dims, strides, box, es, CU_TENSOR_MAP_INTERLEAVE_NONE, sw,
        sw == CU_TENSOR_MAP_SWIZZLE_128B ? CU_TENSOR_MAP_L2_PROMOTION_L2_128B : CU_TENSOR_MAP_L2_PROMOTION_NONE, CU_TENSOR_MAP_FLOAT_OOB_FILL_NONE);
}

template <typename... KArgs, typename... Args>
static void launch(void (*kern)(KArgs...), int grid, int block, int smem, int cluster, bool pdl, Args... args) {
    cudaLaunchConfig_t cfg = {};
    cfg.gridDim = dim3(grid); cfg.blockDim = dim3(block); cfg.dynamicSmemBytes = smem; cfg.stream = cudaStreamPerThread;
    cudaLaunchAttribute at[2];
    int n = 0;
    if (cluster > 1) { at[n].id = cudaLaunchAttributeClusterDimension; at[n].val.clusterDim.x = cluster; at[n].val.clusterDim.y = 1; at[n].val.clusterDim.z = 1; n++; }
    if (pdl) { at[n].id = cudaLaunchAttributeProgrammaticStreamSerialization; at[n].val.programmaticStreamSerializationAllowed = 1; n++; }
    cfg.attrs = at; cfg.numAttrs = n;
    cudaLaunchKernelEx(&cfg, kern, KArgs(args)...);
}

struct HostState {
    bool ready = false;
    const void* key[4] = {nullptr, nullptr, nullptr, nullptr};
    CUtensorMap mX[2], mRes[2], mW, mWr, mWo, mOut, mFin, mResA;
    bf16 *x1T, *x2T;
};

extern "C" void kernel_launch(void* const* d_in, const int* in_sizes, int n_in, void* d_out, int out_size) {
    const bf16* x = (const bf16*)d_in[0];
    const bf16* wqkv = (const bf16*)d_in[1];
    const bf16* wo = (const bf16*)d_in[2];
    const bf16* lar = (const bf16*)d_in[4];
    const bf16* aim = (const bf16*)d_in[5];
    const bf16* cre = (const bf16*)d_in[6];
    const bf16* cim = (const bf16*)d_in[7];
    const bf16* logdt = (const bf16*)d_in[8];
    const bf16* dskip = (const bf16*)d_in[9];
    static HostState hs;
    if (!hs.ready || hs.key[0] != wqkv || hs.key[1] != wo || hs.key[2] != x || hs.key[3] != d_out) {
        void* fn = nullptr;
        cudaDriverEntryPointQueryResult qr;
        cudaGetDriverEntryPoint("cuTensorMapEncodeTiled", &fn, cudaEnableDefault, &qr);
        EncodeTiledFn enc = (EncodeTiledFn)fn;
        cudaGetSymbolAddress((void**)&hs.x1T, g_x1T);
        cudaGetSymbolAddress((void**)&hs.x2T, g_x2T);
        {
            cuuint64_t d[3] = {DM, SEQ / 2, 2}, s[2] = {DM * 4, DM * 2};
            cuuint32_t b[3] = {64, 64, 2}, ba[3] = {64, 64, 1}, br[3] = {16, 64, 1};
            make_map(enc, &hs.mX[0], x, 3, d, s, b, CU_TENSOR_MAP_SWIZZLE_128B);
            make_map(enc, &hs.mResA, x, 3, d, s, ba, CU_TENSOR_MAP_SWIZZLE_128B);
            make_map(enc, &hs.mRes[0], x, 3, d, s, br, CU_TENSOR_MAP_SWIZZLE_32B);
            cuuint64_t d2[3] = {SEQ / 2, DM, 2}, s2[2] = {XP * 2, SEQ};
            cuuint32_t b2[3] = {64, 80, 2};
            make_map(enc, &hs.mX[1], hs.x2T, 3, d2, s2, b, CU_TENSOR_MAP_SWIZZLE_128B);
            make_map(enc, &hs.mRes[1], hs.x2T, 3, d2, s2, b2, CU_TENSOR_MAP_SWIZZLE_128B);
            cuuint64_t d3[2] = {SEQ, DM};
            make_map(enc, &hs.mOut, hs.x1T, 2, d3, s2, b2, CU_TENSOR_MAP_SWIZZLE_128B);
        }
        { cuuint64_t d[2] = {3 * DM, DM}, s[1] = {3 * DM * 2}; cuuint32_t b[2] = {64, 32};
          make_map(enc, &hs.mW, wqkv, 2, d, s, b, CU_TENSOR_MAP_SWIZZLE_128B); }
        { cuuint64_t d[3] = {DM, DM, 3}, s[2] = {3 * DM * 2, DM * 2}; cuuint32_t b[3] = {16, 32, 3};
          make_map(enc, &hs.mWr, wqkv, 3, d, s, b, CU_TENSOR_MAP_SWIZZLE_32B); }
        { cuuint64_t d[4] = {8, 8, DM / 8, DM / 8}, s[3] = {DM * 2, 16, DM * 16}; cuuint32_t b[4] = {8, 8, 10, 5};
          make_map(enc, &hs.mWo, wo, 4, d, s, b, CU_TENSOR_MAP_SWIZZLE_NONE); }
        { cuuint64_t d[3] = {DM, SEQ / 16, 16}, s[2] = {DM * 32, DM * 2}; cuuint32_t b[3] = {80, 8, 16};
          make_map(enc, &hs.mFin, d_out, 3, d, s, b, CU_TENSOR_MAP_SWIZZLE_NONE); }
        cudaFuncSetAttribute(fused_kernel, cudaFuncAttributeMaxDynamicSharedMemorySize, Q_SMEM);
        hs.key[0] = wqkv; hs.key[1] = wo; hs.key[2] = x; hs.key[3] = d_out;
        hs.ready = true;
    }
    const SsmParams sp = {lar, aim, cre, cim, logdt, dskip};
    launch(fused_kernel, 128, 384, Q_SMEM, 2, false, sp, hs.mX[0], hs.mX[1], hs.mW, hs.mWr, hs.mRes[0], hs.mRes[1], hs.mOut, hs.mWo, hs.mFin, hs.mResA);
}
```

```cpp
#include <cuda_runtime.h>
#include <cuda.h>
#include <cuda_bf16.h>
#include <cuda_fp16.h>
#include <stdint.h>

typedef __nv_bfloat16 bf16;

constexpr int SEQ = 2048;
constexpr int DM  = 640;
constexpr int XP  = SEQ + 64;
constexpr int NMODE = 192;

__device__ __forceinline__ uint32_t s2u(const void* p) { return (uint32_t)__cvta_generic_to_shared(p); }
__device__ __forceinline__ void mbar_init(uint32_t b, int c) { asm volatile("mbarrier.init.shared::cta.b64 [%0], %1;" ::"r"(b), "r"(c)); }
__device__ __forceinline__ void mbar_expect(uint32_t b, uint32_t bytes) { asm volatile("mbarrier.arrive.expect_tx.shared::cta.b64 _, [%0], %1;" ::"r"(b), "r"(bytes) : "memory"); }
__device__ __forceinline__ void mbar_arrive(uint32_t b) { asm volatile("mbarrier.arrive.shared::cta.b64 _, [%0];" ::"r"(b) : "memory"); }
__device__ __forceinline__ void mbar_arrive_cta(uint32_t b, uint32_t cta) {
    asm volatile("{\n.reg .b32 ra;\nmapa.shared::cluster.u32 ra, %0, %1;\nmbarrier.arrive.shared::cluster.b64 _, [ra];\n}" ::"r"(b), "r"(cta) : "memory");
}
__device__ __forceinline__ void mbar_wait(uint32_t b, uint32_t ph) {
#ifdef M_PLAIN
    asm volatile("{\n.reg .pred p;\nW: mbarrier.try_wait.parity.shared::cta.b64 p, [%0], %1;\n@!p bra W;\n}" ::"r"(b), "r"(ph) : "memory");
    return;
#endif
    asm volatile("{\n.reg .pred p;\n.reg .u32 n;\nmbarrier.try_wait.parity.shared::cta.b64 p, [%0], %1;\n@p bra D;\nmov.u32 n, 0;\n"
                 "W: mbarrier.try_wait.parity.shared::cta.b64 p, [%0], %1;\n@p bra D;\nadd.u32 n, n, 1;\nsetp.lt.u32 p, n, 4194304;\n@p bra W;\ntrap;\nD:\n}"
                 ::"r"(b), "r"(ph) : "memory");
}
__device__ __forceinline__ void fence_mbar_init() { asm volatile("fence.mbarrier_init.release.cluster;" ::: "memory"); }
__device__ __forceinline__ void cluster_sync() { asm volatile("barrier.cluster.arrive.aligned;\nbarrier.cluster.wait.aligned;" ::: "memory"); }
__device__ __forceinline__ void pdl_wait() { asm volatile("griddepcontrol.wait;" ::: "memory"); }
__device__ __forceinline__ void pdl_launch() { asm volatile("griddepcontrol.launch_dependents;" ::: "memory"); }
__device__ __forceinline__ void named_bar(int id, int n) { asm volatile("bar.sync %0, %1;" ::"r"(id), "r"(n) : "memory"); }
__device__ __forceinline__ void fence_async_smem() { asm volatile("fence.proxy.async.shared::cta;" ::: "memory"); }

__device__ __forceinline__ void tma2d(uint32_t dst, const CUtensorMap* m, int c0, int c1, uint32_t bar) {
    asm volatile("cp.async.bulk.tensor.2d.shared::cluster.global.mbarrier::complete_tx::bytes [%0], [%1, {%3, %4}], [%2];"
                 ::"r"(dst), "l"(m), "r"(bar), "r"(c0), "r"(c1) : "memory");
}
__device__ __forceinline__ void tma2d_mc(uint32_t dst, const CUtensorMap* m, int c0, int c1, uint32_t bar, uint16_t mask) {
    asm volatile("cp.async.bulk.tensor.2d.shared::cluster.global.mbarrier::complete_tx::bytes.multicast::cluster [%0], [%1, {%3, %4}], [%2], %5;"
                 ::"r"(dst), "l"(m), "r"(bar), "r"(c0), "r"(c1), "h"(mask) : "memory");
}
__device__ __forceinline__ void tma3d(uint32_t dst, const CUtensorMap* m, int c0, int c1, int c2, uint32_t bar) {
    asm volatile("cp.async.bulk.tensor.3d.shared::cluster.global.mbarrier::complete_tx::bytes [%0], [%1, {%3, %4, %5}], [%2];"
                 ::"r"(dst), "l"(m), "r"(bar), "r"(c0), "r"(c1), "r"(c2) : "memory");
}
__device__ __forceinline__ void tma3d_mc(uint32_t dst, const CUtensorMap* m, int c0, int c1, int c2, uint32_t bar, uint16_t mask) {
    asm volatile("cp.async.bulk.tensor.3d.shared::cluster.global.mbarrier::complete_tx::bytes.multicast::cluster [%0], [%1, {%3, %4, %5}], [%2], %6;"
                 ::"r"(dst), "l"(m), "r"(bar), "r"(c0), "r"(c1), "r"(c2), "h"(mask) : "memory");
}
__device__ __forceinline__ void bulk_g2s(uint32_t dst, const void* src, uint32_t bytes, uint32_t bar) {
    asm volatile("cp.async.bulk.shared::cluster.global.mbarrier::complete_tx::bytes [%0], [%1], %2, [%3];"
                 ::"r"(dst), "l"(src), "r"(bytes), "r"(bar) : "memory");
}
__device__ __forceinline__ void bulk_g2s_mc(uint32_t dst, const void* src, uint32_t bytes, uint32_t bar, uint16_t mask) {
    asm volatile("cp.async.bulk.shared::cluster.global.mbarrier::complete_tx::bytes.multicast::cluster [%0], [%1], %2, [%3], %4;"
                 ::"r"(dst), "l"(src), "r"(bytes), "r"(bar), "h"(mask) : "memory");
}
__device__ __forceinline__ void prefetch_l2(const void* p, uint32_t bytes) { asm volatile("cp.async.bulk.prefetch.L2.global [%0], %1;" ::"l"(p), "r"(bytes) : "memory"); }
__device__ __forceinline__ void prefetch_tmap(const CUtensorMap* m) { asm volatile("prefetch.tensormap [%0];" ::"l"(m) : "memory"); }

__device__ __forceinline__ void wg_fence() { asm volatile("wgmma.fence.sync.aligned;" ::: "memory"); }
__device__ __forceinline__ void wg_commit() { asm volatile("wgmma.commit_group.sync.aligned;" ::: "memory"); }
template <int N> __device__ __forceinline__ void wg_wait() { asm volatile("wgmma.wait_group.sync.aligned %0;" ::"n"(N) : "memory"); }
__device__ __forceinline__ uint64_t mkdesc(uint32_t addr, uint32_t lbo, uint32_t sbo, uint32_t mode) {
    return (uint64_t)((addr & 0x3FFFF) >> 4) | ((uint64_t)(lbo >> 4) << 16) | ((uint64_t)(sbo >> 4) << 32) | ((uint64_t)mode << 62);
}

__device__ __forceinline__ void mma16816(float (&c)[4], uint32_t a0, uint32_t a1, uint32_t a2, uint32_t a3, uint32_t b0, uint32_t b1) {
    asm("mma.sync.aligned.m16n8k16.row.col.f32.bf16.bf16.f32 {%0,%1,%2,%3},{%4,%5,%6,%7},{%8,%9},{%0,%1,%2,%3};"
                 : "+f"(c[0]), "+f"(c[1]), "+f"(c[2]), "+f"(c[3]) : "r"(a0), "r"(a1), "r"(a2), "r"(a3), "r"(b0), "r"(b1));
}
__device__ __forceinline__ void mma1688(float (&c)[4], uint32_t a0, uint32_t a1, uint32_t b0) {
    asm("mma.sync.aligned.m16n8k8.row.col.f32.bf16.bf16.f32 {%0,%1,%2,%3},{%4,%5},{%6},{%0,%1,%2,%3};"
                 : "+f"(c[0]), "+f"(c[1]), "+f"(c[2]), "+f"(c[3]) : "r"(a0), "r"(a1), "r"(b0));
}
__device__ __forceinline__ void ldsm_x4(uint32_t& r0, uint32_t& r1, uint32_t& r2, uint32_t& r3, uint32_t a) {
    asm volatile("ldmatrix.sync.aligned.m8n8.x4.shared.b16 {%0,%1,%2,%3}, [%4];" : "=r"(r0), "=r"(r1), "=r"(r2), "=r"(r3) : "r"(a) : "memory");
}
__device__ __forceinline__ void ldsm_x4_t(uint32_t& r0, uint32_t& r1, uint32_t& r2, uint32_t& r3, uint32_t a) {
    asm volatile("ldmatrix.sync.aligned.m8n8.x4.trans.shared.b16 {%0,%1,%2,%3}, [%4];" : "=r"(r0), "=r"(r1), "=r"(r2), "=r"(r3) : "r"(a) : "memory");
}
__device__ __forceinline__ void ldsm_x2(uint32_t& r0, uint32_t& r1, uint32_t a) {
    asm volatile("ldmatrix.sync.aligned.m8n8.x2.shared.b16 {%0,%1}, [%2];" : "=r"(r0), "=r"(r1) : "r"(a) : "memory");
}
__device__ __forceinline__ void ldsm_x2_t(uint32_t& r0, uint32_t& r1, uint32_t a) {
    asm volatile("ldmatrix.sync.aligned.m8n8.x2.trans.shared.b16 {%0,%1}, [%2];" : "=r"(r0), "=r"(r1) : "r"(a) : "memory");
}
__device__ __forceinline__ void stsm_x4(uint32_t a, uint32_t r0, uint32_t r1, uint32_t r2, uint32_t r3) {
    asm volatile("stmatrix.sync.aligned.m8n8.x4.shared.b16 [%0], {%1,%2,%3,%4};" ::"r"(a), "r"(r0), "r"(r1), "r"(r2), "r"(r3) : "memory");
}
__device__ __forceinline__ void stsm_x4_t(uint32_t a, uint32_t r0, uint32_t r1, uint32_t r2, uint32_t r3) {
    asm volatile("stmatrix.sync.aligned.m8n8.x4.trans.shared.b16 [%0], {%1,%2,%3,%4};" ::"r"(a), "r"(r0), "r"(r1), "r"(r2), "r"(r3) : "memory");
}
__device__ __forceinline__ void stsm_x2(uint32_t a, uint32_t r0, uint32_t r1) {
    asm volatile("stmatrix.sync.aligned.m8n8.x2.shared.b16 [%0], {%1,%2};" ::"r"(a), "r"(r0), "r"(r1) : "memory");
}
__device__ __forceinline__ uint32_t movm_t(uint32_t a) {
    uint32_t d;
    asm volatile("movmatrix.sync.aligned.m8n8.trans.b16 %0, %1;" : "=r"(d) : "r"(a));
    return d;
}
__device__ __forceinline__ uint32_t lds32(uint32_t a) { uint32_t v; asm volatile("ld.shared.u32 %0, [%1];" : "=r"(v) : "r"(a) : "memory"); return v; }
__device__ __forceinline__ uint32_t ldsv32(uint32_t a) { uint32_t v; asm volatile("ld.volatile.shared.u32 %0, [%1];" : "=r"(v) : "r"(a) : "memory"); return v; }
__device__ __forceinline__ void sts32(uint32_t a, uint32_t v) { asm volatile("st.shared.u32 [%0], %1;" ::"r"(a), "r"(v) : "memory"); }
__device__ __forceinline__ uint4 lds128(uint32_t a) { uint4 v; asm volatile("ld.shared.v4.u32 {%0,%1,%2,%3}, [%4];" : "=r"(v.x), "=r"(v.y), "=r"(v.z), "=r"(v.w) : "r"(a) : "memory"); return v; }
__device__ __forceinline__ void sts128(uint32_t a, uint4 v) { asm volatile("st.shared.v4.u32 [%0], {%1,%2,%3,%4};" ::"r"(a), "r"(v.x), "r"(v.y), "r"(v.z), "r"(v.w) : "memory"); }

__device__ __forceinline__ void stg128(void* p, uint4 v) { asm volatile("st.global.v4.u32 [%0], {%1,%2,%3,%4};" ::"l"(p), "r"(v.x), "r"(v.y), "r"(v.z), "r"(v.w) : "memory"); }

__device__ __forceinline__ uint4 ldg128(const void* p) { uint4 v; asm volatile("ld.global.v4.u32 {%0,%1,%2,%3}, [%4];" : "=r"(v.x), "=r"(v.y), "=r"(v.z), "=r"(v.w) : "l"(p) : "memory"); return v; }
__device__ __forceinline__ uint2 ldg64(const void* p) { uint2 v; asm volatile("ld.global.v2.u32 {%0,%1}, [%2];" : "=r"(v.x), "=r"(v.y) : "l"(p) : "memory"); return v; }
__device__ __forceinline__ uint32_t ldg32(const void* p) { uint32_t v; asm volatile("ld.global.u32 %0, [%1];" : "=r"(v) : "l"(p) : "memory"); return v; }

__device__ __forceinline__ uint32_t pack2(float lo, float hi) {
    uint32_t r;
    asm("cvt.rn.bf16x2.f32 %0, %1, %2;" : "=r"(r) : "f"(hi), "f"(lo));
    return r;
}
__device__ __forceinline__ float bf_lo(uint32_t v) { return __uint_as_float(v << 16); }
__device__ __forceinline__ float bf_hi(uint32_t v) { return __uint_as_float(v & 0xFFFF0000u); }
__device__ __forceinline__ float rbf(float x) { return __uint_as_float(pack2(0.f, x) & 0xFFFF0000u); }
__device__ __forceinline__ float ex2(float x) { float r; asm("ex2.approx.ftz.f32 %0, %1;" : "=f"(r) : "f"(x)); return r; }

__device__ __forceinline__ float2 ln_finish(float sum, float sumsq) {
    const float m = sum * (1.0f / DM);
    const float v = fmaxf(fmaf(sumsq, 1.0f / DM, -m * m), 0.f);
    float s, r;
    asm("sqrt.approx.ftz.f32 %0, %1;" : "=f"(s) : "f"(rbf(rbf(v) + 1e-5f)));
    asm("rcp.approx.ftz.f32 %0, %1;" : "=f"(r) : "f"(rbf(s)));
    return make_float2(m, r);
}
__device__ __forceinline__ uint32_t ln_finish_packed(float sum, float sumsq) {
    const float m = sum * (1.0f / DM);
    const float v = fmaxf(fmaf(sumsq, 1.0f / DM, -m * m), 0.f);
    float s;
    asm("sqrt.approx.ftz.f32 %0, %1;" : "=f"(s) : "f"(rbf(rbf(v) + 1e-5f)));
    return pack2(s, m);
}
__device__ __forceinline__ float frsq(float x) { float r; asm("rsqrt.approx.ftz.f32 %0, %1;" : "=f"(r) : "f"(x)); return r; }
__device__ __forceinline__ float frcp(float x) { float r; asm("rcp.approx.ftz.f32 %0, %1;" : "=f"(r) : "f"(x)); return r; }
__device__ __forceinline__ bool elect_one() {
    uint32_t p;
    asm volatile("{\n.reg .pred p;\nelect.sync _|p, 0xffffffff;\nselp.u32 %0, 1, 0, p;\n}" : "=r"(p));
    return p != 0;
}
__device__ __forceinline__ void cluster_arrive_relaxed() { asm volatile("barrier.cluster.arrive.relaxed.aligned;" ::: "memory"); }
__device__ __forceinline__ void cluster_wait() { asm volatile("barrier.cluster.wait.aligned;" ::: "memory"); }
__device__ __forceinline__ unsigned long long ld_ll(const unsigned long long* p) {
    unsigned long long v;
    asm volatile("ld.relaxed.gpu.global.b64 %0, [%1];" : "=l"(v) : "l"(p) : "memory");
    return v;
}
__device__ __forceinline__ void st_ll(unsigned long long* p, uint32_t payload, uint32_t tag) {
    const unsigned long long v = (unsigned long long)payload | ((unsigned long long)tag << 32);
    asm volatile("st.relaxed.gpu.global.b64 [%0], %1;" ::"l"(p), "l"(v) : "memory");
}
__device__ __forceinline__ uint4 ld_ll4(const uint4* p) {
    uint4 v;
    asm volatile("{\n.reg .b128 t;\n.reg .b64 a, b;\nld.relaxed.gpu.global.b128 t, [%4];\nmov.b128 {a, b}, t;\nmov.b64 {%0, %1}, a;\nmov.b64 {%2, %3}, b;\n}"
                 : "=r"(v.x), "=r"(v.y), "=r"(v.z), "=r"(v.w) : "l"(p) : "memory");
    return v;
}
__device__ __forceinline__ void st_ll4(uint4* p, uint32_t x, uint32_t y, uint32_t z, uint32_t w) {
    asm volatile("{\n.reg .b128 t;\n.reg .b64 a, b;\nmov.b64 a, {%1, %2};\nmov.b64 b, {%3, %4};\nmov.b128 t, {a, b};\nst.relaxed.gpu.global.b128 [%0], t;\n}"
                 ::"l"(p), "r"(x), "r"(y), "r"(z), "r"(w) : "memory");
}

__device__ __forceinline__ void bulk_s2g(void* dst, uint32_t src, uint32_t bytes) {
    asm volatile("cp.async.bulk.global.shared::cta.bulk_group [%0], [%1], %2;" ::"l"(dst), "r"(src), "r"(bytes) : "memory");
}
__device__ __forceinline__ void bulk_commit() { asm volatile("cp.async.bulk.commit_group;" ::: "memory"); }
__device__ __forceinline__ void bulk_wait() { asm volatile("cp.async.bulk.wait_group 0;" ::: "memory"); }
__device__ __forceinline__ void fence_async_global() { asm volatile("fence.proxy.async.global;" ::: "memory"); }
__device__ __forceinline__ void fence_release() { asm volatile("fence.release.gpu;" ::: "memory"); }
__device__ __forceinline__ void fence_acquire() { asm volatile("fence.acquire.gpu;" ::: "memory"); }
template<int TA, int TB>
__device__ __forceinline__ void wgmma_n192(float (&d)[96], uint64_t da, uint64_t db, int scale_d) {
  asm volatile("{\n.reg .pred p;\nsetp.ne.b32 p, %98, 0;\n"
    "wgmma.mma_async.sync.aligned.m64n192k16.f32.bf16.bf16 "
    "{%0, %1, %2, %3, %4, %5, %6, %7, %8, %9, %10, %11, %12, %13, %14, %15, %16, %17, %18, %19, %20, %21, %22, %23, %24, %25, %26, %27, %28, %29, %30, %31, %32, %33, %34, %35, %36, %37, %38, %39, %40, %41, %42, %43, %44, %45, %46, %47, %48, %49, %50, %51, %52, %53, %54, %55, %56, %57, %58, %59, %60, %61, %62, %63, %64, %65, %66, %67, %68, %69, %70, %71, %72, %73, %74, %75, %76, %77, %78, %79, %80, %81, %82, %83, %84, %85, %86, %87, %88, %89, %90, %91, %92, %93, %94, %95}, %96, %97, p, 1, 1, %99, %100;\n}\n"
    : "+f"(d[0]), "+f"(d[1]), "+f"(d[2]), "+f"(d[3]), "+f"(d[4]), "+f"(d[5]), "+f"(d[6]), "+f"(d[7]), "+f"(d[8]), "+f"(d[9]), "+f"(d[10]), "+f"(d[11]), "+f"(d[12]), "+f"(d[13]), "+f"(d[14]), "+f"(d[15]), "+f"(d[16]), "+f"(d[17]), "+f"(d[18]), "+f"(d[19]), "+f"(d[20]), "+f"(d[21]), "+f"(d[22]), "+f"(d[23]), "+f"(d[24]), "+f"(d[25]), "+f"(d[26]), "+f"(d[27]), "+f"(d[28]), "+f"(d[29]), "+f"(d[30]), "+f"(d[31]), "+f"(d[32]), "+f"(d[33]), "+f"(d[34]), "+f"(d[35]), "+f"(d[36]), "+f"(d[37]), "+f"(d[38]), "+f"(d[39]), "+f"(d[40]), "+f"(d[41]), "+f"(d[42]), "+f"(d[43]), "+f"(d[44]), "+f"(d[45]), "+f"(d[46]), "+f"(d[47]), "+f"(d[48]), "+f"(d[49]), "+f"(d[50]), "+f"(d[51]), "+f"(d[52]), "+f"(d[53]), "+f"(d[54]), "+f"(d[55]), "+f"(d[56]), "+f"(d[57]), "+f"(d[58]), "+f"(d[59]), "+f"(d[60]), "+f"(d[61]), "+f"(d[62]), "+f"(d[63]), "+f"(d[64]), "+f"(d[65]), "+f"(d[66]), "+f"(d[67]), "+f"(d[68]), "+f"(d[69]), "+f"(d[70]), "+f"(d[71]), "+f"(d[72]), "+f"(d[73]), "+f"(d[74]), "+f"(d[75]), "+f"(d[76]), "+f"(d[77]), "+f"(d[78]), "+f"(d[79]), "+f"(d[80]), "+f"(d[81]), "+f"(d[82]), "+f"(d[83]), "+f"(d[84]), "+f"(d[85]), "+f"(d[86]), "+f"(d[87]), "+f"(d[88]), "+f"(d[89]), "+f"(d[90]), "+f"(d[91]), "+f"(d[92]), "+f"(d[93]), "+f"(d[94]), "+f"(d[95])
    : "l"(da), "l"(db), "r"(scale_d), "n"(TA), "n"(TB));
}

template<int TA, int TB>
__device__ __forceinline__ void wgmma_n48(float (&d)[24], uint64_t da, uint64_t db, int scale_d) {
  asm volatile("{\n.reg .pred p;\nsetp.ne.b32 p, %26, 0;\n"
    "wgmma.mma_async.sync.aligned.m64n48k16.f32.bf16.bf16 "
    "{%0, %1, %2, %3, %4, %5, %6, %7, %8, %9, %10, %11, %12, %13, %14, %15, %16, %17, %18, %19, %20, %21, %22, %23}, %24, %25, p, 1, 1, %27, %28;\n}\n"
    : "+f"(d[0]), "+f"(d[1]), "+f"(d[2]), "+f"(d[3]), "+f"(d[4]), "+f"(d[5]), "+f"(d[6]), "+f"(d[7]), "+f"(d[8]), "+f"(d[9]), "+f"(d[10]), "+f"(d[11]), "+f"(d[12]), "+f"(d[13]), "+f"(d[14]), "+f"(d[15]), "+f"(d[16]), "+f"(d[17]), "+f"(d[18]), "+f"(d[19]), "+f"(d[20]), "+f"(d[21]), "+f"(d[22]), "+f"(d[23])
    : "l"(da), "l"(db), "r"(scale_d), "n"(TA), "n"(TB));
}

__device__ __forceinline__ void wgmma_rs80(float (&d)[40], const uint4& a, uint64_t db, int scale_d) {
  asm volatile("{\n.reg .pred p;\nsetp.ne.b32 p, %45, 0;\n"
    "wgmma.mma_async.sync.aligned.m64n80k16.f32.bf16.bf16 {%0,%1,%2,%3,%4,%5,%6,%7,%8,%9,%10,%11,%12,%13,%14,%15,%16,%17,%18,%19,%20,%21,%22,%23,%24,%25,%26,%27,%28,%29,%30,%31,%32,%33,%34,%35,%36,%37,%38,%39}, {%40,%41,%42,%43}, %44, p, 1, 1, 1;\n}\n"
    : "+f"(d[0]), "+f"(d[1]), "+f"(d[2]), "+f"(d[3]), "+f"(d[4]), "+f"(d[5]), "+f"(d[6]), "+f"(d[7]), "+f"(d[8]), "+f"(d[9]), "+f"(d[10]), "+f"(d[11]), "+f"(d[12]), "+f"(d[13]), "+f"(d[14]), "+f"(d[15]), "+f"(d[16]), "+f"(d[17]), "+f"(d[18]), "+f"(d[19]), "+f"(d[20]), "+f"(d[21]), "+f"(d[22]), "+f"(d[23]), "+f"(d[24]), "+f"(d[25]), "+f"(d[26]), "+f"(d[27]), "+f"(d[28]), "+f"(d[29]), "+f"(d[30]), "+f"(d[31]), "+f"(d[32]), "+f"(d[33]), "+f"(d[34]), "+f"(d[35]), "+f"(d[36]), "+f"(d[37]), "+f"(d[38]), "+f"(d[39])
    : "r"(a.x), "r"(a.y), "r"(a.z), "r"(a.w), "l"(db), "r"(scale_d));
}

__device__ const __align__(1024) uint32_t c_fft[11264] = {
0x2ddc2dba,0x2fe62eb5,0x2ed02eb5,0xafffaf6e,0x2e1f2dfe,0x2e3f2fbc,0x2f022ee9,0xad27af30,0x2e5e2e3f,0x1fd92b5e,0x2f302f1a,0x244ea875,0x2e992e7c,0xad96a993,0x2f5a2f46,0x2e992c32,
0xad00ad72,0xa17eac32,0xa17ea515,0xabb79cb6,0xac07ac87,0x2dfe29f1,0x1fd99648,0xafedae99,0xa9f1ab05,0x2fd42fbc,0x26a1244e,0xad96af91,0xa765a8d5,0x2aaa2e3f,0x29932875,0x2515a8d5,
0xae99adfe,0xb000aee9,0xaf6eafbc,0x2c872f30,0xaf80af1a,0xac32af02,0xae7caf02,0xaaaa217e,0xaff4afc9,0x2b5e9cb6,0xad27addc,0xaff4ae7c,0xafedb000,0x2ffc2eb5,0xab05ac5d,0xacd8af5a,
0x2c072d27,0x9fd92bb7,0xadfead00,0x2fed2e1f,0x25db2993,0xaf6eacb0,0xaf6eaed0,0x2c5d2f46,0xa5151648,0xaddcafdd,0xafffafd4,0xac321648,0xabb7a934,0x28d5a814,0xafa0afed,0xaff4af30,
0x2f302e3f,0x2fed2f1a,0x28142b5e,0x2934a875,0x30002fc9,0x26a12ddc,0xa5db1cb6,0x30002e7c,0x2f462fd4,0xaed0aa4e,0xacb0aa4e,0x29932e99,0x2d272e5e,0xae3faffc,0xaf02adfe,0xae1fa814,
0xa9f1acd8,0x26a1ab05,0x2fd42ffc,0xad96afed,0x2515a30e,0x2fff2e1f,0x2ddc2f1a,0x2c32a30e,0x2d272aaa,0x28752e7c,0x28752c32,0x2fa02f80,0x2f912e99,0xaee9a9f1,0xa8141648,0x9fd92c87,
0xafa0ae7c,0xafafaf46,0x2d002993,0xafa0ac32,0xaf91b000,0x244eac5d,0x2fbc2eb5,0xab05af5a,0xac87ae5e,0x30002dfe,0x2f6e2ffc,0x2e992814,0x1cb6a875,0x25152e1f,0x2c322e1f,0x2d722ff4,
0x27652c87,0xa9932a4e,0xaaaaadba,0xa5152c87,0xabb7a44e,0xafa0af30,0x28d59fd9,0xaff4ae5e,0xaf91ae1f,0x2814abb7,0x2ee92d00,0x1fd9ad27,0xaf5aafff,0x2fd42ed0,0x2fd42fe6,0x30002ddc,
0x2f462f6e,0x2c322fdd,0x2e7c2fdd,0xa993b000,0xab5e2934,0xafafacd8,0xad00244e,0x2f1a2dfe,0xaee9afaf,0x2f30a17e,0xadfeaff8,0xafbca30e,0x2c5da765,0xa9f12ddc,0x2d969cb6,0x2c5dacb0,
0x2bb7a993,0x2f1aa515,0x2f1a2765,0xaff4aaaa,0x2e5e2fd4,0xab052dba,0x29342f6e,0x2ee9a6a1,0xadba1fd9,0xa5dbafed,0xafddac07,0xaa4e2dfe,0xacb0aff8,0x2ddc2f02,0x9cb6ae3f,0xa765aff8,
0xaeb5af91,0xaa4eafed,0x9648ae5e,0xac5d2d4d,0x2ddca17e,0x2e7c2e3f,0x2fc92e3f,0x1cb6afa0,0x2bb72fe6,0xaff8a993,0xab5e2aaa,0x2bb72fc9,0xafbcaa4e,0x2f30a5db,0xadfeafdd,0xaee9adba,
0xacd828d5,0xaf91230e,0xaf30af02,0x2c072fa0,0xac5dafff,0x2dbaac32,0x2dbaa515,0xae99addc,0x2fc929f1,0xa9932eb5,0x2aaa2fdd,0x2fe629f1,0xa30e2dfe,0xa17eafed,0xaff8ac07,0xafaf1fd9,
0x2dfe2faf,0x28142ff8,0xae5e217e,0x2ffc230e,0xaf5aa515,0xac87af46,0xa6a1af80,0xaf5a2765,0x1cb6ae99,0x2e7c2dba,0x2fc92dba,0x2ddcac5d,0x2f1a2ee9,0xafafab05,0xad002934,0xab5e2e5e,
0x2dbaa814,0x2fdd9fd9,0x25db2f91,0x2a4eaee9,0x27652faf,0xaf4628d5,0xaf80ae1f,0xa5152faf,0xafa0addc,0x2e3fac32,0x2e3fa515,0xa17eafff,0x2dfea6a1,0xacd82dba,0x244e2f6e,0x29342fd4,
0xad27afc9,0xa30eafff,0x2faf2d72,0xad27ae7c,0x2ffc2a4e,0x28142fdd,0xae5e25db,0x2dfe2dba,0xac5d2c07,0xaa4eaf91,0x9648af30,0xaeb5acd8,0xa993aff4,0x2c322f1a,0x2e7c2f1a,0x2f462bb7,
0xae7c26a1,0xafff1648,0x2d72aa4e,0xafc926a1,0x230eaee9,0x2ff89fd9,0x217e2f91,0x2fafa814,0x2d4d2fa0,0xafed230e,0xae5eaf02,0xaf9128d5,0xb000aaaa,0x2fdda515,0x2fdd2765,0x2f6ea993,
0x9cb63000,0xacb02fd4,0xa7652fd4,0x2ddcaf5a,0x217eaffc,0x2ff4ac07,0x2875afbc,0xaff82934,0xa44e2ff4,0xadfea8d5,0xa9342fa0,0x2cd82bb7,0x25dbafe6,0x16482f46,0x29f1af80,0x25dbafc9,
0x2ff41cb6,0x2e1f2765,0x2e1f2cb0,0xa875addc,0xafbca5db,0x1fd9af5a,0xad4dad96,0xacd82fdd,0x2f5a2934,0xaeb52ee9,0x2c5d2e5e,0x3000ab05,0xaed0ab5e,0x2f80a30e,0xaaaaaf02,0xacb0ab5e,
0x25dbaffc,0x2d96afbc,0x2f5aac07,0xafdd2934,0xaaaa2fa0,0xafc92875,0xafe62875,0x29932d27,0x2d00aed0,0x28d52d72,0x2ff89cb6,0x2d00afe6,0xae5e2d96,0x2d4dafd4,0xaf91a6a1,0xafed29f1,
0xafbca17e,0xad4da875,0x1fd9aff4,0xacd82ff8,0x2e992aaa,0xaa4e2fe6,0xaa4e2fc9,0x2fd4a993,0xacb0ad96,0x2fffac87,0x2d72aeb5,0xa765ad96,0x28752f30,0xab5eac07,0xaf1a2cd8,0xae3f2f91,
0xa9342ff4,0xae5e2fa0,0xaee9a8d5,0x2b052bb7,0x2d96aed0,0x2eb59cb6,0x2c872d72,0x2d96afe6,0xaf802c5d,0x2765af6e,0xa515af6e,0xaf4625db,0x2ff8a44e,0xaff42d4d,0xa8752ffc,0xa17e2ee9,
0x2f5a244e,0x2c5d2934,0xaeb52dfe,0x3000acd8,0xacb0ad00,0x2d72aff8,0x2fffa8d5,0xa765ad00,0x217e2f80,0xaf022515,0xaf02a765,0xaf1a2f46,0x2b05afdd,0xa8142f5a,0x2c072d96,0x2d4d25db,
0x2b5eafe6,0x2f02af80,0x230e2f46,0x2b5eafc9,0xaf302d96,0xacd8a6a1,0x2c07afd4,0xaf9129f1,0x2fdda44e,0xad962ffc,0xaf5a2d4d,0xa5db2ee9,0xad72abb7,0x2e7ca17e,0x2fc9a17e,0x2fffad00,
0xaed0a5db,0xaaaaa9f1,0x2f809648,0xacb0a5db,0x28752e5e,0xaf1a2f91,0xab5ead4d,0xae3f2fed,0x2b05aff8,0x2c072875,0xa8142ff4,0x2d4d217e,0xaf6e2d72,0x2eb5afc9,0x2eb5ae7c,0x2dbaafff,
0xaf802f5a,0xafc92e99,0xafe62e99,0x2f46ad96,0x28d52b05,0xaf022fed,0x230e2cd8,0x2fa0affc,0x2fbcaf02,0xa9342d27,0x2ffcae1f,0x2c07ae3f,0xa6a1ac32,0x2a4e9cb6,0x9648ad72,0xa6a1a515,
0x28752aaa,0xa8d52cb0,0xa8d52ed0,0x2e3faf80,0x2fedaeb5,0x29349648,0x2f30aa4e,0x2814ac5d,0x1648ad4d,0x2e99acd8,0x2c87afbc,0xa9f11fd9,0xafe62d27,0x2fffafaf,0xaddc230e,0xaed02d27,
0x2fd4af30,0x2f6eae5e,0x2dbaa44e,0xa6a19fd9,0x1cb6ad27,0x2fe6aff4,0x2ed0aff4,0xad722b5e,0xafaf2cb0,0x2e1faf46,0xa8d5a993,0xafaf2ed0,0xac072f6e,0x2934ac87,0xaffc2e99,0xafbc3000,
0xa44eab5e,0x2b05ad00,0x2f91afaf,0xafbc2f1a,0xafd42d72,0x1648a765,0x1648acb0,0xafdd2fff,0xac322f5a,0xaaaa26a1,0xaf802c87,0xae7c2f5a,0x2d009fd9,0xae1f2cd8,0xad272fbc,0xabb72d4d,
0xaffc2f02,0xaee92e1f,0x244ead27,0xad4d2e3f,0xa9f12e7c,0xafdd2f80,0xaeb52aaa,0xa9f12c32,0x2d72a5db,0xafe63000,0xaed03000,0x9cb626a1,0x2fa0afbc,0xaf022f91,0x230e2b05,0x28d5a44e,
0x96482c07,0xac872d4d,0xae992b05,0x29f1a814,0x2ed0abb7,0xa9932b5e,0xaf462ff8,0x2cb0abb7,0x2f1aafff,0xa30e2765,0xa30e2cb0,0x2e1fad72,0x1fd9ac5d,0x244e9648,0x2e5eaa4e,0x2f30aeb5,
0x2ff8aed0,0x2e3faddc,0xaf022fff,0x2ff8afe6,0x2d4daf6e,0x2ee9ae99,0xa44e2c87,0x2ffcb000,0xa6a1a814,0x2f6eaf30,0x2dbaa934,0x2fd4afed,0xaf462d00,0x2fc9afa0,0x2fe6afa0,0x2f80afaf,
0x2515ac5d,0x2d72ad96,0x1cb629f1,0x2c32ac5d,0xad002814,0x2d27ad4d,0x2e1fab05,0x2bb7ac07,0xaffc2f1a,0x2cd8ad00,0x2fedafaf,0x2b05ab5e,0xadba2f80,0x2c87acb0,0x2c87aed0,0x2a4eaaaa,
0x2f802f6e,0x2fc92fdd,0x2fe62fdd,0xaf46b000,0x2fa02f91,0x2bb72e5e,0x2ff42fed,0xa8d5ad4d,0x2fbc2faf,0xa934217e,0x2ffc2ff8,0x2c07230e,0x2fd42fc9,0xaf5aad72,0x30002fff,0x2fd42e7c,
0x2bb72aaa,0x2f1a2cb0,0x2f1a2ed0,0xaff4af80,0x2cd82c5d,0x2f303000,0x2f912f5a,0xac07aeb5,0x2dba2d4d,0x25db2cd8,0x2fdd2fbc,0x2a4e9fd9,0x2e7c2e1f,0xad72a875,0x2fff2ff4,0x2fc92e1f,
0xa6a1a934,0x29f1a44e,0x2d962cd8,0xafd4adfe,0x1cb6a17e,0x2fe62e3f,0x2ed02e3f,0xad72afa0,0x28752515,0x2d272f80,0x2fa02f46,0x2875a765,0x2c072a4e,0xa93425db,0x2ffc2fdd,0x2fbc2dba,
0xae5eaf1a,0xa934ae3f,0x2b052875,0xaee9ab5e,0xac5dad72,0x2dba2765,0x2dba2cb0,0xae99afff,0xa765aa4e,0x2f802fd4,0x2f462e99,0x2515aa4e,0x230e9fd9,0x217e2cd8,0x2ff82fbc,0x2faf2d4d,
0xaffcafaf,0xaee9aff8,0x244ea17e,0xad4da30e,0xaf6eafe6,0x25dbaaaa,0x2c5d2993,0xaf6eafc9,0xad72ae99,0x2fe62dba,0x2ed02dba,0x1cb6ac5d,0xa8d5ac07,0x2bb72f30,0x2ff42f91,0x2fa02cd8,
0xadbaac07,0xafddad4d,0xa5dbab05,0xaa4e2814,0xafc9af02,0xaaaaaf1a,0x2993217e,0xafe6af02,0xafa0afff,0x2e3f2765,0x2e3f2cb0,0xa17ead72,0xad4daeb5,0x2e5e3000,0x2fed2f5a,0x2f912c5d,
0xa17e2765,0xad001cb6,0xabb7addc,0xa17e2cb0,0xad4daa4e,0xaee9afdd,0x244ea5db,0xaffcadba,0xafd4aee9,0x29f1a934,0x2d962b05,0xa6a1ae5e,0xaf46aff4,0x2fc92f1a,0x2fe62f1a,0x2f802bb7,
0x2cb02eb5,0x1cb62dba,0xaddcaf6e,0x27652eb5,0xa30e2814,0xaff8ad4d,0xa17eab05,0xafafac07,0xadfeab5e,0xa44eae3f,0x2cd82875,0xa934af1a,0xb000af80,0x2fdd2cb0,0x2fdd2ed0,0x2f6e2aaa,
0x2d723000,0x25152fd4,0x2c322fd4,0x1cb6af5a,0xae1f9fd9,0xae3faee9,0xaf02a814,0x2d272f91,0xacd8aff4,0x2ffc28d5,0xab05afa0,0xafedabb7,0x2e992515,0xad962aaa,0x2f5a2993,0x2e99a765,
0x2ff42ddc,0x2e1f2ed0,0x2e1f2fe6,0xa875afff,0xa8142c87,0xaffca9f1,0xadfe1648,0x2e5e2e99,0xaf5aaf30,0x2eb5a814,0xac5dafed,0xb000a934,0x2c32a8d5,0xa9932e3f,0x2f462875,0x2e7ca8d5,
0x2e991fd9,0x30002814,0x2f6e2ee9,0xac87af91,0x29932fa0,0xaed02875,0xacb02875,0x2f462d27,0xaff4ac32,0x2b5eaddc,0xad27afff,0xaff4a515,0x244ead96,0x1fd92fd4,0x2f3026a1,0x2e5ea9f1,
0x2814ad27,0x2dfeabb7,0x2ffc2d00,0xae5eae1f,0x2e992f80,0xaa4e2e7c,0xaa4e2c32,0x2fd42aaa,0xae7c1648,0x9cb6afdd,0xaddcafd4,0xafc91648,0xa875af91,0x2b5e2fbc,0x2f1a244e,0x2e3fab05,
0xab05aff4,0x244eafa0,0x2fbc28d5,0xaf91abb7,0x30002c32,0x26a12fff,0xa5db2ddc,0x30002515,0xaaaa2c5d,0xac32af6e,0xae7caf6e,0xaf8025db,0xad27afed,0x2e3f2dfe,0x2f021fd9,0x2e1fac07,
0xaf5aae5e,0xac5daf30,0x2eb59fd9,0xb000a44e,0x2e7ca30e,0x2ddc2e1f,0x1cb62f1a,0x2fc9a30e,0x217e2f46,0xaf02acb0,0xaf02aed0,0xaf1a2993,0xaf30ae99,0x2fbc29f1,0x2ee99648,0x2dfeac87,
0xafa0a515,0xafafa993,0x2d00aaaa,0xafa02765,0x2934ad96,0x2fed26a1,0x28142fd4,0x2f30a9f1,0x2c872fed,0xb0009fd9,0xaf6eadfe,0xae992c07,0xafffabb7,0x2fe6a17e,0x2ed0a17e,0x2ddcad00,
0xac322c87,0xaf462a4e,0x2993adba,0xae7c2c87,0xa875afed,0x2f1aab05,0x2b5e2ffc,0x2e3facd8,0x2f302e1f,0xaee92bb7,0xafbcad00,0xadfe2d27,0xaf6e9cb6,0x2eb5ac32,0x2eb5a515,0x2dbaad72,
0xaaaa2f5a,0xaed02e99,0xacb02e99,0x2f80ad96,0x2b5eaf30,0x2fafa44e,0x2d00ae5e,0xaf1a9fd9,0xac072f02,0xab05ad27,0xad4d2e1f,0x28142e3f,0x2c5daed0,0xa9f12fff,0x2d96addc,0x2c5dafe6,
0x28752f80,0xa8d52fe6,0xa8d52fc9,0x2e3faf46,0xa44eafd4,0x2f91adba,0x2b05af6e,0xafbc26a1,0x96482ffc,0xae99a44e,0xac872ee9,0x29f12d4d,0x2515aff8,0x1cb62f02,0x2d72ae3f,0x2c32aff8,
0x2eb52b05,0x2a4e2cd8,0x16482fed,0x2c5daffc,0xad72ad27,0x2cb0aff4,0x2765aff4,0xafff2b5e,0x2bb72e7c,0xaff82aaa,0xab5e2f80,0x2bb72c32,0xa814af6e,0x2b052c87,0x2d4dae99,0x2c07b000,
0x2feda8d5,0x2f30a30e,0x29342f02,0x2814afa0,0xafd49cb6,0x1648aed0,0x1648afe6,0xafdd2d72,0x2ed029f1,0xaf462eb5,0xa9932fdd,0x2cb029f1,0xad00ad4d,0x2e1f244e,0x2d27aee9,0x2bb7affc,
0x2d4daf02,0x2fbcae1f,0x2cd82d27,0x9fd9ae3f,0xaf5a2cb0,0xac87a993,0xa6a1af46,0xaf5a2ed0,0x2fffa5db,0xacb03000,0xa7653000,0x2d7226a1,0xaf1aa814,0x2fafa934,0x2d00af30,0x2b5eafed,
0x1648afbc,0x2c87affc,0x2e992934,0xa9f1ac07,0xac322faf,0xaf8028d5,0xaaaaae1f,0xae7c2faf,0x2f1aad72,0xa30e2ed0,0xa30e2fe6,0x2e1f1cb6,0xaffc26a1,0x2fedadba,0x2cd8af6e,0x2b05afd4,
0xad27ac32,0xa30ead72,0x2faf9cb6,0xad27a515,0x1fd92f6e,0xafbc2e99,0xacd8ac87,0xad4d3000,0x2c5dafbc,0x2a4e2b05,0x16482f91,0x2eb5a44e,0xaf802d00,0x2ed0afa0,0x2cb0afa0,0x2aaaafaf,
0xafe626a1,0xaddc1648,0x2fffaa4e,0xaed026a1,0x2d002c07,0xad272ffc,0xae1fa934,0xabb72fbc,0x1fd9afa0,0x2e5ea30e,0x244e2f02,0x2f30a8d5,0xadba2f46,0x2c87afe6,0x2c87afc9,0x2a4eaf80,
0xafff2d96,0xae7c2c5d,0xafc92c5d,0x2d72a9f1,0xa17e2dfe,0xaff42fbc,0xa8752ee9,0x2ff8af30,0x2fedad00,0xad4d2f1a,0x2f91ab5e,0x2e5eafaf,0x25dbae7c,0x16482993,0x29f1af46,0x25dbac32,
0xae3f2fff,0xaff82fc9,0xaff82e7c,0x2f02ad72,0x2c0725db,0xadfe2f5a,0x9fd92d96,0x2fedafdd,0x2f6eaf91,0xa6a12c07,0x2fd4acd8,0x2dbaaf30,0xa765ab5e,0x2aaaa30e,0x2993af02,0x2515ab5e,
0xa5db2dfe,0xad962ee9,0xaf5a2fbc,0x2fddaf30,0x2f46ab5e,0xa7652bb7,0x25152bb7,0x2f80aff8,0x2d00afc9,0x28d59cb6,0x2ff8addc,0x2d00ae7c,0xacd89648,0x2dfeac5d,0x2934aeb5,0x244eaa4e,
0x2c07217e,0x9fd92875,0xadfe2ff4,0x2fedaff8,0x2fddaf46,0x29f1a515,0x29f12765,0x2eb5af80,0x2515ad96,0x2ddcac87,0x2fffaeb5,0x2c32ad96,0xaf022b05,0x2fa0aee9,0x28d5ae5e,0x230ea934,
0x2f91ad00,0x2cd8ab5e,0xac072f1a,0x2f30afaf,0x2d96afc9,0x2eb5addc,0x2c879cb6,0x2d96ae7c,0xa993a6a1,0x2fc9af5a,0x2fe6af5a,0x2aaaac87,0xaff82e5e,0x2ff4affc,0x2875adfe,0x217ea814,
0x2f6eafed,0x2fd4af91,0xa6a12d4d,0x2dbaae5e,0x2515ad00,0x2fffaff8,0x2ddca8d5,0x2c32ad00,0xae1f2993,0x2fafafe6,0x2fafafc9,0x28d5aaaa,0xaf912fdd,0x2ee9af5a,0x2814ad96,0x1fd9a5db,
0x2b5eae7c,0x2f02af46,0x230e2993,0x2b5eac32,0xab059648,0x2e5eaeb5,0x2ee9ac5d,0x2934aa4e,0xafdd2e5e,0x2d96adfe,0x2f5aaffc,0x25dba814,0xaddc2faf,0x2cb0ad27,0x2765ad27,0x1cb6a30e,
0xa765a5db,0x2993a9f1,0x2aaa9648,0x2515a5db,0xaf022cd8,0x28d5a934,0x2fa0adfe,0x230ea44e,0xaf912ff8,0x2814a875,0x2ee9aff4,0x1fd9a17e,0xaa4e2ddc,0x26a1a765,0x26a1acb0,0x16489cb6,
0x2d722d96,0x25152c5d,0x2c322c5d,0x1cb6a9f1,0x2d272d4d,0xad00a814,0x2bb72c07,0x2e1f2b05,0x2cd82d00,0xaffcaf1a,0x2b052b5e,0x2fed2faf,0x2c872cb0,0xadbaaf80,0x2a4e2aaa,0x2c872ed0,
0x2e3f2ddc,0x2ff82ed0,0x2ff82fe6,0xaf02afff,0x2ee92e99,0x2d4d2f6e,0x2ffc3000,0xa44eac87,0x2f6e2f30,0xa6a12814,0x2fd42fed,0x2dba2934,0x2fc92fa0,0xaf46ad00,0x2f802faf,0x2fe62fa0,
0xac87ad4d,0x9648ac07,0x29f12814,0xae99ab05,0xa993ab5e,0x2ed02bb7,0x2cb02bb7,0xaf46aff8,0xa30ea765,0x2f1a2fff,0x2e1f2d72,0xa30eacb0,0x244e1648,0x1fd92c5d,0x2f302eb5,0x2e5e2a4e,
0xaee9ae1f,0xaffcaf02,0xad4dae3f,0x244e2d27,0xafddaf80,0xa9f1ae7c,0xa9f1ac32,0xaeb5aaaa,0xafe6b000,0x2d7225db,0x9cb6a6a1,0xaed0b000,0xaf02af91,0x2fa02fbc,0x28d5244e,0x230eab05,
0x2b052d00,0xa44e2b5e,0xafbcaf1a,0x2f912faf,0x16482765,0xafd4ad72,0xafddafff,0x16482cb0,0xaaaaa6a1,0xac32af5a,0xae7caf5a,0xaf80ac87,0xae1facd8,0x2d001fd9,0xabb7ad4d,0xad27afbc,
0x2f6e2e5e,0x2fd42f30,0xa6a11fd9,0x2dba244e,0x2fe62ff4,0x1cb62d27,0xad72ab5e,0x2ed02ff4,0x2e1f2f46,0xafafacb0,0xafafaed0,0xa8d52993,0x29342c87,0xac07af6e,0xafbcb000,0xaffcae99,
0xa8d5acb0,0x2875aaaa,0x2e3f2f80,0xa8d5aed0,0x29341648,0x2fed2eb5,0x28142c5d,0x2f302a4e,0x2e992cd8,0x16482d4d,0xa9f19fd9,0x2c872fbc,0x2fff2faf,0xafe6ad27,0xaed0ad27,0xaddca30e,
0xafc9ae99,0xaf80af5a,0x2f462d96,0xafe6ae99,0xaf02afed,0x28d5ab05,0x2fa02ffc,0x230eacd8,0xa934ad27,0x2fbc2f02,0x2c072e3f,0x2ffc2e1f,0x2a4e1cb6,0xa6a12c32,0xa6a12515,0x96482d72,
0xaaaa29f1,0xaed025db,0xacb025db,0x2f801648,0xaf1aaf91,0x2875ae5e,0xae3fafed,0xab5e2d4d,0x2c07a875,0x2b052ff8,0x2d4da17e,0xa814aff4,0x2eb52fc9,0xaf6ead72,0x2dba2fff,0x2eb52e7c,
0x2f022f80,0x2b5e2fe6,0x2b5e2fc9,0x230eaf46,0xacd826a1,0xaf30ad96,0xaf91a9f1,0x2c072fd4,0xad96affc,0x2fdd244e,0xa5dbaee9,0xaf5aad4d,0x2e7c217e,0xad722bb7,0x2fff2d00,0x2fc9217e,
0x2c5da934,0x2f5aa44e,0x30002cd8,0xaeb5adfe,0x2d722ff8,0xacb02d00,0xa7652d00,0x2fff28d5,0xaf02a515,0x217eaf80,0xaf1aaf46,0xaf022765,0xa814af5a,0x2b052fdd,0x2d4da5db,0x2c07ad96,
0xae5eafa0,0xa934aff4,0x2b05abb7,0xaee928d5,0x2eb51cb6,0x2d962ed0,0x2d962fe6,0x2c87ad72,0x27652f6e,0xaf80ac5d,0xaf46a5db,0xa5152f6e,0xaff4ad4d,0x2ff8244e,0xa17eaee9,0xa875affc,
0xad4d2875,0xafbc217e,0xacd8aff8,0x1fd92ff4,0xaa4eafe6,0x2e99aaaa,0x2fd42993,0xaa4eafc9,0x2fff2c87,0xacb02d96,0xa7652d96,0x2d722eb5,0xab5e2c07,0x2875af30,0xae3faf91,0xaf1aacd8,
0x2d962fbc,0x25db2ffc,0xafdda934,0x2f5a2c07,0xafc9a875,0xaaaaafa0,0x2993ad27,0xafe6a875,0x28d5ad72,0x2d002ed0,0x2d002fe6,0x2ff81cb6,0x2d4d2fd4,0xae5ead96,0xafeda9f1,0xaf9126a1,
0x2e1fa765,0x2ff49cb6,0xa8752ddc,0x2e1facb0,0x1fd92f5a,0xafbc25db,0xacd8afdd,0xad4d2d96,0xaeb5aee9,0x2f5aa934,0x30002b05,0x2c5dae5e,0x2f80230e,0xaed02b5e,0xacb02b5e,0xaaaa2f02,
0xacb0afd4,0x9cb6b000,0x2ddc2f5a,0xa765afd4,0x2ff42c07,0x217e2ffc,0xaff8a934,0x28752fbc,0xadfe28d5,0xa44eaff4,0x2cd8abb7,0xa934afa0,0x1648af46,0x25db2fe6,0x25db2fc9,0x29f12f80,
0xafff9648,0xae7ca6a1,0xafc9a6a1,0x2d722a4e,0x2ff81fd9,0x230e2ee9,0x2faf2814,0x217eaf91,0xafeda30e,0x2d4dafa0,0xaf91a8d5,0xae5e2f02,0x2fdd2515,0xb0002aaa,0x2f6e2993,0x2fdda765,
0xa30e2fff,0xad272fc9,0xad272e7c,0x2fafad72,0x2814afdd,0x2ffcaa4e,0x2dfeadba,0xae5ea5db,0xaa4e2f91,0xac5dac07,0xaeb52cd8,0x96482f30,0x2c32af1a,0xa9932ff4,0x2f46abb7,0x2e7caf1a,
0x2fdd1fd9,0x2dba2814,0x2a4e2ee9,0x25dbaf91,0xaf46a8d5,0x2765afaf,0xa515afaf,0xaf802e1f,0x2e3f2c32,0xafa02ddc,0xa17e2fff,0x2e3f2515,0xacd8adba,0x2dfe26a1,0x2934afd4,0x244eaf6e,
0x2814aff8,0x2dfeafaf,0x2ffca30e,0xae5ea17e,0xac872f46,0xaf5a2515,0xaf5aa765,0xa6a12f80,0x2e7cadba,0x1cb62e99,0x2ddc2c5d,0x2fc9adba,0xafaf2b05,0x2f1aaee9,0xab5eae5e,0xad00a934,
0xaf91a30e,0xacd8a8d5,0x2c07afa0,0xaf302f02,0x2dba2c32,0xac5d2fff,0xae992ddc,0x2dba2515,0xa993aeb5,0x2fc9a9f1,0x2fe6a9f1,0x2aaaafdd,0xa17e2fed,0xa30eadfe,0xafaf9fd9,0xaff82c07,
0xaa4e2fed,0xaeb52f91,0xac5dad4d,0x96482e5e,0x2e7cae3f,0x2ddc217e,0x1cb62fa0,0x2fc9ae3f,0xaff82993,0x2bb7afe6,0x2bb7afc9,0xab5eaaaa,0x2f3025db,0xafbc2a4e,0xaee92dba,0xadfe2fdd,
0x2f1a2515,0x2bb72993,0xaff42aaa,0x2f1aa765,0xab05adba,0x2e5eafd4,0x2ee926a1,0x2934af6e,0xa5db2fed,0xadba9fd9,0xaa4eadfe,0xafdd2c07,0x2ddcaf02,0xacb02ff8,0xa7652ff8,0x9cb62e3f,
0x2c32afdd,0x2f46af6e,0xa9933000,0x2e7cafdd,0xafaf2cd8,0xab5ea934,0x2f1aadfe,0xad00a44e,0x2f30217e,0xaee92faf,0xafbc230e,0xadfe2ff8,0xa9f1addc,0x2c5d2765,0x2c5d2cb0,0x2d961cb6,
0xa993aa4e,0x2765ac87,0xa515ac87,0xaaaa2dba,0xafa02f30,0xabb7244e,0xaff42e5e,0x28d51fd9,0x28142bb7,0xaf912e1f,0x1fd92d27,0x2ee9ad00,0x2fd4aed0,0xaf5a2fff,0x3000addc,0x2fd4afe6,
0xafaf2f46,0xafa02e7c,0xafa02c32,0x2d00a993,0x244e2c5d,0xaf913000,0xab052f5a,0x2fbcaeb5,0x3000adfe,0xac872e5e,0x2e99a814,0x2f6eaffc,0x2515ae1f,0x1cb62875,0x2d72aff4,0x2c32ae1f,
0x26a12b05,0xa9f12cd8,0xad962fed,0x2fd4affc,0x2fffae1f,0x2515230e,0x2c32230e,0x2ddcaf1a,0x2875ae7c,0x2d27aaaa,0x2fa0af80,0x2875ac32,0xaee929f1,0x2f91ae99,0x9fd9ac87,0xa8149648,
0x2fedaf1a,0x2f30ae3f,0x29342875,0x2814ab5e,0x26a1addc,0x3000afc9,0x3000ae7c,0xa5db9cb6,0xaed02a4e,0x2f46afd4,0x2993ae99,0xacb02a4e,0xae3f2ffc,0x2d27ae5e,0xae1f2814,0xaf022dfe,
0x9fd9abb7,0x2c07ad27,0x2fedae1f,0xadfe2d00,0xaf6e2cb0,0x25dba993,0x2c5daf46,0xaf6e2ed0,0xaddc2fdd,0xa5159648,0xac329648,0xafff2fd4,0x28d52814,0xabb72934,0xaff42f30,0xafa02fed,
0xb0002ee9,0xae992dfe,0x2c87af30,0xaf6e2fbc,0xac322f02,0xaf802f1a,0xaaaaa17e,0xae7c2f02,0x2b5e1cb6,0xaff42fc9,0xaff42e7c,0xad272ddc,0x2ffcaeb5,0xafed3000,0xacd82f5a,0xab052c5d,
0xa17e2c32,0xad002d72,0xabb71cb6,0xa17e2515,0x2dfea9f1,0xac072c87,0xafed2e99,0x1fd91648,0x2fd4afbc,0xa9f12b05,0xad962f91,0x26a1a44e,0x2aaaae3f,0xa76528d5,0x251528d5,0x2993a875,
0x2fe6aeb5,0x2ddcadba,0xafff2f6e,0x2ed0aeb5,0x2e3fafbc,0x2e1fadfe,0xad272f30,0x2f02aee9,0x1fd9ab5e,0x2e5eae3f,0x244e2875,0x2f30af1a,0xad962993,0x2e99ae7c,0x2e99ac32,0x2f5aaf46,
0x299329f1,0xa76525db,0x251525db,0x2aaa1648,0x28d52934,0xaf02acd8,0x230e244e,0x2fa02dfe,0x28142875,0xaf91aff8,0x1fd9217e,0x2ee92ff4,0x26a12765,0xaa4eaddc,0x16481cb6,0x26a12cb0,
0x2f022f46,0x2b5e2e7c,0x2b5e2c32,0x230ea993,0x2e5e2eb5,0xab051648,0x29342a4e,0x2ee92c5d,0x2d962dfe,0xafddae5e,0x25db2814,0x2f5a2ffc,0x2cb02d27,0xaddcafaf,0x1cb6230e,0x27652d27,
0x2fd42f91,0x2f6e2fed,0x2dba2e5e,0xa6a1ad4d,0x2fff2ff8,0x25152d00,0x2c322d00,0x2ddc28d5,0x2faf2fe6,0xae1fa993,0x28d52aaa,0x2faf2fc9,0x2ee92f5a,0xaf91afdd,0x1fd925db,0x28142d96,
0x2cd82b5e,0x2f912d00,0x2f302faf,0xac07af1a,0x2eb52ddc,0x2d962fc9,0x2d962e7c,0x2c871cb6,0x2fc92f5a,0xa99326a1,0x2aaa2c87,0x2fe62f5a,0x2ff42ffc,0xaff8ae5e,0x217e2814,0x28752dfe,
0x9fd9a875,0x2c07a17e,0x2fed2ff8,0xadfeaff4,0x29f12515,0x2fdd2f46,0x2eb52f80,0x29f1a765,0x2ddc2c87,0x25152d96,0x2c322d96,0x2fff2eb5,0x2fa02ee9,0xaf02ab05,0x230e2934,0x28d52e5e,
0xad96aee9,0xa5dbadfe,0x2fdd2f30,0xaf5aafbc,0xa765abb7,0x2f462b5e,0x2f802ff8,0x2515abb7,0x28d51cb6,0x2d002fc9,0x2d002e7c,0x2ff82ddc,0x2dfe2c5d,0xacd81648,0x244e2a4e,0x29342eb5,
0xaff8afc9,0xae3fafff,0x2f022d72,0xaff8ae7c,0xadfeaf5a,0x2c07a5db,0x2fed2fdd,0x9fd9ad96,0xa6a1ac07,0x2f6e2f91,0x2dba2f30,0x2fd42cd8,0x2aaa230e,0xa7652b5e,0x25152b5e,0x29932f02,
0xae7cac5d,0xafffad96,0x2d7229f1,0xafc9ac5d,0xaff4afbc,0xa17eadfe,0x2ff82f30,0xa875aee9,0xad4daf1a,0x2fed2d00,0x2e5e2faf,0x2f912b5e,0x1648a993,0x25db2e7c,0x25db2c32,0x29f12f46,
0xaddc9648,0xafe6a6a1,0xaed0a6a1,0x2fff2a4e,0xad27affc,0x2d00ac07,0xabb7afbc,0xae1f2934,0x2e5e230e,0x1fd92fa0,0x2f3028d5,0x244eaf02,0x2c872fe6,0xadbaaf46,0x2a4e2f80,0x2c872fc9,
0xa30e2d72,0xad272c32,0xad272515,0x2faf1cb6,0xafbcae99,0x1fd9af6e,0xad4db000,0xacd82c87,0x2a4eab05,0x2c5d2fbc,0x2eb5244e,0x1648af91,0x2ed02fa0,0xaf80ad00,0x2aaa2faf,0x2cb02fa0,
0x2c872ffc,0x16482fbc,0xa9f12c07,0x2e99a934,0xaf80a8d5,0xac32afaf,0xae7cafaf,0xaaaa2e1f,0xa30eaed0,0x2f1a2d72,0x2e1f9cb6,0xa30eafe6,0x2fed2dba,0xaffca6a1,0x2b052fd4,0x2cd82f6e,
0x2fbc2e1f,0x2d4d2f02,0x9fd92e3f,0x2cd8ad27,0xac872993,0xaf5aacb0,0xaf5aaed0,0xa6a12f46,0xacb0b000,0x2fff25db,0x2d72a6a1,0xa765b000,0x2faf2934,0xaf1a2814,0x2b5e2fed,0x2d002f30,
0x2f30230e,0x2fed28d5,0x28142fa0,0x2934af02,0x16482ed0,0xafd41cb6,0xafddad72,0x16482fe6,0xaf46aeb5,0x2ed0a9f1,0x2cb0a9f1,0xa993afdd,0x2e1fa44e,0xad002d4d,0x2bb72ffc,0x2d272ee9,
0x2a4eacd8,0x2eb5ab05,0x2c5d2ffc,0x1648afed,0x2cb02ff4,0xad722d27,0xafffab5e,0x27652ff4,0xaff8aaaa,0x2bb7ae7c,0x2bb7ac32,0xab5eaf80,0x2b05ac87,0xa8142f6e,0x2c073000,0x2d4d2e99,
0xa8d5afe6,0x2875af80,0x2e3f2f46,0xa8d5afc9,0x2f912dba,0xa44e2fd4,0xafbca6a1,0x2b052f6e,0xae99244e,0x9648affc,0x29f1ad4d,0xac87aee9,0x1cb6af02,0x25152ff8,0x2c322ff8,0x2d722e3f,
0xaed0ae99,0xaaaaaf5a,0x2f802d96,0xacb0ae99,0x2faf244e,0x2b5e2f30,0xaf1a1fd9,0x2d002e5e,0xab052d27,0xac07af02,0x2814ae3f,0xad4dae1f,0xa9f1afff,0x2c5d2ed0,0x2c5d2fe6,0x2d962ddc,
0xaf46aa4e,0xac32ac87,0xae7cac87,0x29932dba,0x2f1a2b05,0xa8752fed,0x2e3f2cd8,0x2b5eaffc,0xaee9abb7,0x2f30ae1f,0xadfead27,0xafbc2d00,0x2eb52c32,0xaf6e1cb6,0x2dba2d72,0x2eb52515,
0xafaf2993,0xafa02515,0xafa0a765,0x2d002aaa,0x2feda6a1,0x29342d96,0x2f3029f1,0x2814afd4,0xb0001fd9,0x2c87afed,0xae99ac07,0xaf6e2dfe,0x2fe6217e,0xafff2bb7,0x2ddc2d00,0x2ed0217e,
0xac5d2f30,0xaf5a2e5e,0xb000244e,0x2eb51fd9,0x2ddcae1f,0x2e7c230e,0x2fc9230e,0x1cb6af1a,0xaf022cb0,0x217eaf46,0xaf1aa993,0xaf022ed0,0x2fbca9f1,0xaf302e99,0x2dfe2c87,0x2ee91648,
0x244e2fa0,0xab052ff4,0xaf912bb7,0x2fbca8d5,0x26a1afff,0x3000ac32,0x3000a515,0xa5dbaddc,0xac322f6e,0xaaaaac5d,0xaf80a5db,0xae7c2f6e,0x2e3fadfe,0xad272fed,0x2e1f2c07,0x2f029fd9,
0x2dfe2bb7,0x28142d27,0xae5e2e1f,0x2ffcad00,0xaa4eae7c,0x2e99af80,0x2fd4aaaa,0xaa4eac32,0x9cb62fdd,0xae7c9648,0xafc99648,0xaddc2fd4,0x2b5eafbc,0xa8752f91,0x2e3f2b05,0x2f1aa44e,
0x3000a814,0x2e999fd9,0xac872f91,0x2f6eaee9,0xaed0a875,0x2993afa0,0x2f46ad27,0xacb0a875,0x2b5e2ddc,0xaff42c32,0xaff42515,0xad272fff,0x1fd9afd4,0x244e2d96,0x2e5e29f1,0x2f30a6a1,
0x2e1faed0,0x2ff4addc,0xa8752fff,0x2e1fafe6,0xaffc29f1,0xa814ac87,0x2e5eae99,0xadfe9648,0x2eb52814,0xaf5a2f30,0xb0002934,0xac5d2fed,0xa993ae3f,0x2c3228d5,0x2e7c28d5,0x2f46a875,
0x2515afd4,0x2d72b000,0x1cb62f5a,0x2c32afd4,0xae3f2ee9,0xae1f1fd9,0x2d27af91,0xaf022814,0x2ffca8d5,0xacd82ff4,0xafed2bb7,0xab052fa0,0xad96aaaa,0x2e99a515,0x2e992765,0x2f5aa993,
0x1cb6adba,0x2cb0aeb5,0x2765aeb5,0xaddc2f6e,0xaff82d4d,0xa30ea814,0xafaf2c07,0xa17e2b05,0xa44e2e3f,0xadfe2b5e,0xa9342f1a,0x2cd8a875,0x2fddacb0,0xb0002f80,0x2f6eaaaa,0x2fddaed0,
0xad009cb6,0xa17ea765,0xa17eacb0,0xabb72ddc,0xaee92fdd,0xad4d2a4e,0xaffc2dba,0x244e25db,0x29f12934,0xafd42ee9,0xa6a12e5e,0x2d96ab05,0x2fc9af1a,0xaf462ff4,0x2f80abb7,0x2fe6af1a,
0xafdd2d4d,0xadba2c07,0xaa4ea814,0xa5db2b05,0xaaaa2f1a,0xafc92f02,0xafe62f02,0x2993a17e,0x2e3fa765,0xafa02fff,0xa17e2d72,0x2e3facb0,0x2e5eb000,0xad4d2eb5,0x2f91ac5d,0x2fedaf5a,
0xaee92ff8,0xaffc2faf,0xad4d230e,0x244e217e,0x25db2aaa,0xaf6e2fe6,0xaf6e2fc9,0x2c5da993,0x2fe6adba,0xad722e99,0x1cb62c5d,0x2ed0adba,0x2bb7af30,0xa8d52c07,0x2fa0acd8,0x2ff4af91,
0xa9342e3f,0xae5e2f1a,0xaee92b5e,0x2b05a875,0x2dbaa765,0xac5d2d72,0xae992fff,0x2dbaacb0,0x2f80afd4,0xa7652a4e,0x25152a4e,0x2f46ae99,0x217eacd8,0x230e1fd9,0x2fafad4d,0x2ff8afbc,
0x29f1244e,0xa6a12934,0xafd42dfe,0x2d96acd8,0x2fe6ae3f,0x1cb6217e,0xad722fa0,0x2ed0ae3f,0x2d27af80,0x2875a515,0x28752765,0x2fa0af46,0xa934a5db,0x2c07aa4e,0x2fbcadba,0x2ffcafdd,
0x2f1aacb0,0x2bb7aaaa,0xaff42f80,0x2f1aaed0,0x2f30b000,0x2cd8ac5d,0xac072eb5,0x2f91af5a,0x25dbacd8,0x2dbaad4d,0x2a4e1fd9,0x2fddafbc,0xad722875,0x2e7cae1f,0x2fc9ae1f,0x2fffaff4,
0x2fc9afdd,0x2f80af6e,0xaf463000,0x2fe6afdd,0x2bb7ae5e,0x2fa0af91,0xa8d52d4d,0x2ff4afed,0xa934a17e,0x2fbcafaf,0x2c07a30e,0x2ffcaff8,0xaf5a2d72,0x2fd4afc9,0x2fd4ae7c,0x3000afff,
0x9d4d9e16,0xada6ae7d,0x9b769c84,0xabf0accf,0x985299e4,0xa897aa43,0x90b6957f,0xa102a5d8,0x13db0a48,0x242c1aad,0x191b1712,0x296d2783,0x1c201aad,0x2c632b1a,0x1db21ce9,0x2e112d3a,
0xa3f4a491,0xae51af42,0xa199a2c6,0xac70ad60,0x9e7ba06b,0xa922ab00,0x97129c20,0xa199a688,0x19e410b6,0x24aa1b76,0x1fa81d4d,0x2a112833,0x222f2102,0x2ce82bf0,0x2445235d,0x2ec92dd8,
0xa6a1a79c,0xaefcb004,0xa4aaa5a5,0xace8adf2,0xa166a35d,0xa9acabbe,0x99e49edf,0xa22fa738,0x1ce913db,0x25281c20,0x2262206b,0x2ab528a4,0x2528242c,0x2d6d2c63,0x271f2623,0x2f822e77,
0xa8a4a954,0xafa8b067,0xa688a7e8,0xad60ae84,0xa38fa528,0xaa37ac3d,0x9c20a0d0,0xa2c6a7e8,0x1edf157f,0x25a51c84,0x2478222f,0x2b592915,0x273825d8,0x2df22ccf,0x28fc284c,0x301d2f16,
0xa9f8aadb,0xb02ab0ca,0xa833a915,0xadd8af16,0xa4dca6a1,0xaac1ac9c,0x9d4da22f,0xa35da84c,0x206b1712,0x26231ce9,0x25bf23f4,0x2bfd2987,0x28a42783,0x2e772d3a,0x2a692987,0x307a2fb5,
0xab4cac31,0xb081b12e,0xa922aa37,0xae51afa8,0xa5f1a80d,0xab4cacfb,0x9e7ba38f,0xa3f4a8a4,0x21661852,0x26a11d4d,0x270524dc,0x2c5029f8,0x29ac2897,0x2efc2da6,0x2bd72ac1,0x30d7302a,
0xac50acf5,0xb0d7b192,0xaa11ab59,0xaec9b01d,0xa705a8ca,0xabd7ad5a,0x9fa8a478,0xa445a8fc,0x2262191b,0x271f1db2,0x282625bf,0x2ca22a69,0x2ab5296d,0x2f822e11,0x2ca22bfd,0x3135307a,
0xacfbadb9,0xb12eb1f7,0xab00ac3d,0xaf42b067,0xa80da987,0xac31adb9,0xa06ba528,0xa491a954,0x235d19e4,0x279c1e16,0x28ca26a1,0x2cf52adb,0x2bbe2a43,0x30042e7d,0x2d5a2c9c,0x319230ca,
0xb185b25c,0xb426b4cc,0xafbbb0b1,0xb1c6b306,0xac76ae18,0xaea3b08a,0xa4dca9ac,0xa738ac37,0x280d1e7b,0x2a0520d0,0x2d472b4c,0x2fdb2d6d,0x30472ee9,0x32663128,0x31f0311b,0x347933a8,
0xb1ddb2c1,0xb453b501,0xb01ab0fb,0xb204b352,0xacbcae77,0xaee9b0ba,0xa528aa05,0xa783ac63,0x284c1edf,0x2a432102,0x2d992bbe,0x30172da6,0x308a2f55,0x32aa315f,0x324f316b,0x34aa33fc,
0xb235b327,0xb481b537,0xb057b145,0xb242b39e,0xad01aed6,0xaf2fb0eb,0xa573aa5d,0xa7cfac90,0x288b1f44,0x2a822134,0x2deb2c18,0x30412ddf,0x30ce2fc2,0x32ef3196,0x32ae31bc,0x34db3428,
0xb28db38e,0xb4afb56d,0xb094b18f,0xb280b3eb,0xad47af36,0xaf75b11b,0xa5bfaab5,0xa80dacbc,0x28ca1fa8,0x2ac12166,0x2e3e2c50,0x306a2e18,0x31113017,0x333531cd,0x330d320e,0x350d3452,
0xb2e5b3f5,0xb4ddb5a3,0xb0d1b1da,0xb2beb41c,0xad8caf95,0xafbbb14b,0xa60aab0d,0xa833ace8,0x29092006,0x2b002199,0x2e902c89,0x30942e51,0x3155304d,0x337a3204,0x336d325f,0x3540347c,
0xb33eb42e,0xb50cb5da,0xb10eb224,0xb2fcb443,0xadd2aff5,0xb001b17c,0xa655ab65,0xa859ad14,0x29482039,0x2b4021cb,0x2ee32cc2,0x30be2e8a,0x31993084,0x33c0323b,0x33cd32b1,0x357234a6,
0xb398b463,0xb53ab612,0xb14bb26f,0xb33bb469,0xae18b02a,0xb024b1ac,0xa6a1abbe,0xa87ead40,0x2987206b,0x2b7f21fd,0x2f362cfb,0x30e72ec3,0x31dd30ba,0x34033273,0x34173303,0x35a534d1,
0xb3f2b497,0xb569b64a,0xb189b2bb,0xb37ab490,0xae5eb05a,0xb047b1dd,0xa6ecac0b,0xa8a4ad6d,0x29c6209d,0x2bbe222f,0x2f882d34,0x31112efc,0x322130f1,0x342632aa,0x34483356,0x35d934fc,
0xb599b682,0xb722b82e,0xb3b9b4b7,0xb4ddb5f9,0xb06ab20e,0xb185b398,0xa8caad99,0xa9f8aefc,0x2bfd2262,0x2cfb23f4,0x313b2f36,0x328d3081,0x344932e2,0x35693453,0x360d3527,0x37bd368b,
0xb5c9b6bb,0xb755b84d,0xb3f8b4df,0xb4feb622,0xb08db23e,0xb1a9b3ca,0xa8f0adc5,0xaa1eaf29,0x2c1e2294,0x2d1b2413,0x31652f6f,0x32b7309d,0x346d331a,0x358e3470,0x36413553,0x37f536ba,
0xb5f9b6f5,0xb789b86d,0xb41cb506,0xb51fb64c,0xb0b1b26f,0xb1cdb3fc,0xa915adf2,0xaa43af55,0x2c3d22c6,0x2d3a242c,0x318f2fa8,0x32e230ba,0x34903352,0x35b3348d,0x3676357e,0x381736e8,
0xb629b72f,0xb7bdb88d,0xb43cb52e,0xb540b676,0xb0d4b2a1,0xb1f0b417,0xa93bae1e,0xaa69af82,0x2c5d22f9,0x2d5a2445,0x31b92fe2,0x330d30d7,0x34b4338b,0x35d934aa,0x36ab35ab,0x38343717,
0xb65ab76a,0xb7f1b8ad,0xb45cb556,0xb561b6a0,0xb0f7b2d2,0xb214b430,0xa961ae4b,0xaa8fafaf,0x2c7d232b,0x2d79245f,0x31e3300e,0x333830f4,0x34d833c3,0x35fe34c7,0x36e035d7,0x38513746,
0xb68bb7a5,0xb813b8ce,0xb47cb57e,0xb582b6ca,0xb11bb303,0xb238b449,0xa987ae77,0xaab5afdb,0x2c9c235d,0x2d992478,0x320e302a,0x33633111,0x34fc33fc,0x362434e4,0x37173604,0x386f3775,
0xb6bdb7e2,0xb82eb8f0,0xb49cb5a7,0xb5a3b6f5,0xb13eb335,0xb25cb463,0xa9acaea3,0xaadbb004,0x2cbc238f,0x2db92491,0x32383047,0x338e312e,0x3520341a,0x364a3501,0x374d3631,0x388d37a5,
0xb6efb80f,0xb849b911,0xb4bdb5d0,0xb5c5b720,0xb162b366,0xb280b47c,0xa9d2aed0,0xab00b01a,0x2cdb23c2,0x2dd824aa,0x32623064,0x33b9314b,0x35453437,0x3670351f,0x3785365e,0x38ab37d6,
0xb865b934,0xb94dba5c,0xb5e7b74c,0xb6fcb85a,0xb2a4b495,0xb3c6b564,0xab26b031,0xac2bb0e4,0x2df824c3,0x2ef6258c,0x33e43168,0x34a13252,0x3697353c,0x37d4362d,0x38ca3803,0x39d038d0,
0xb880b957,0xb96bba84,0xb609b777,0xb720b872,0xb2c8b4af,0xb3ebb57e,0xab4cb047,0xac3db0fb,0x2e1824dc,0x2f1625a5,0x34083185,0x34b7326f,0x36bd355a,0x37fd364c,0x38e9381c,0x39f338eb,
0xb89cb97a,0xb98abaad,0xb62bb7a4,0xb744b88a,0xb2ecb4c9,0xb408b599,0xab72b05d,0xac50b111,0x2e3724f5,0x2f3625bf,0x341e31a2,0x34ce328d,0x36e43577,0x3813366b,0x39093835,0x3a173906,
0xb8b9b99e,0xb9aabad7,0xb64db7d0,0xb768b8a2,0xb310b4e2,0xb41ab5b3,0xab98b074,0xac63b128,0x2e57250f,0x2f5525d8,0x343331c0,0x34e432aa,0x370b3595,0x3828368a,0x3929384e,0x3a3b3922,
0xb8d6b9c3,0xb9cabb02,0xb670b7fd,0xb78cb8ba,0xb335b4fc,0xb42db5ce,0xabbeb08a,0xac76b13e,0x2e772528,0x2f7525f1,0x344931dd,0x34fa32c8,0x373335b3,0x383d36a9,0x39493868,0x3a60393e,
0xb8f3b9e8,0xb9ebbb2d,0xb693b815,0xb7b1b8d2,0xb359b516,0xb43fb5e9,0xabe3b0a1,0xac89b155,0x2e972541,0x2f95260a,0x345f31fa,0x351132e5,0x375b35d2,0x385236c8,0x396a3881,0x3a86395a,
0xb910ba0e,0xba0cbb59,0xb6b6b82c,0xb7d6b8eb,0xb37db530,0xb452b604,0xac05b0b7,0xac9cb16b,0x2eb6255a,0x2fb52623,0x34753217,0x35273303,0x378335f0,0x386836e8,0x398c389b,0x3aac3977,
0xb92eba35,0xba2dbb87,0xb6d9b843,0xb7fbb904,0xb3a2b54a,0xb464b61e,0xac18b0ce,0xacafb182,0x2ed62573,0x2fd5263c,0x348b3235,0x353e3321,0x37ab360e,0x387d3708,0x39ae38b6,0x3ad33994,
0x9ce99db2,0xad3aae11,0x9aad9c20,0xab1aac63,0x9712991b,0xa783a96d,0x8a4893db,0x9aada42c,0x157f10b6,0x25d82102,0x19e41852,0x2a432897,0x1c841b76,0x2ccf2bf0,0x1e161d4d,0x2e7d2da6,
0xa35da445,0xadd8aec9,0xa102a22f,0xabf0ace8,0x9d4d9fa8,0xa833aa11,0x90b699e4,0x9b76a4aa,0x1c201712,0x26882199,0x206b1e7b,0x2b002922,0x22c62199,0x2d602c70,0x249123f4,0x2f422e51,
0xa623a71f,0xae77af82,0xa42ca528,0xac63ad6d,0xa06ba262,0xa8a4aab5,0x93db9ce9,0x9c20a528,0x1edf19e4,0x2738222f,0x235d2166,0x2bbe29ac,0x25a524aa,0x2df22ce8,0x279c26a1,0x30042efc,
0xa84ca8fc,0xaf16b01d,0xa5d8a738,0xaccfadf2,0xa22fa478,0xa915ab59,0x957f9edf,0x9c84a5a5,0x20d01c20,0x27e822c6,0x2528238f,0x2c3d2a37,0x27e82688,0x2e842d60,0x295428a4,0x30672fa8,
0xa987aa69,0xafb5b07a,0xa783a8a4,0xad3aae77,0xa3f4a5bf,0xa987abfd,0x9712a06b,0x9ce9a623,0x222f1d4d,0x284c235d,0x26a124dc,0x2c9c2ac1,0x29152833,0x2f162dd8,0x2adb29f8,0x30ca302a,
0xaac1abd7,0xb02ab0d7,0xa897a9ac,0xada6aefc,0xa4dca705,0xa9f8ac50,0x9852a166,0x9d4da6a1,0x238f1e7b,0x28a423f4,0x280d25f1,0x2cfb2b4c,0x2a372922,0x2fa82e51,0x2c312b4c,0x312e3081,
0xabfdaca2,0xb07ab135,0xa96daab5,0xae11af82,0xa5bfa826,0xaa69aca2,0x991ba262,0x9db2a71f,0x24781fa8,0x28fc2445,0x28ca2705,0x2d5a2bd7,0x2b592a11,0x301d2ec9,0x2cf52c50,0x319230d7,
0xac9cad5a,0xb0cab192,0xaa43abbe,0xae7db004,0xa6a1a8ca,0xaadbacf5,0x99e4a35d,0x9e16a79c,0x2528206b,0x29542491,0x2987280d,0x2db92c31,0x2c3d2b00,0x30672f42,0x2db92cfb,0x31f7312e,
0xb11bb1f0,0xb3a8b479,0xaee9b047,0xb128b266,0xab4cad47,0xad6dafdb,0x9e7ba80d,0xa0d0aa05,0x29ac24dc,0x2c372738,0x2e182c76,0x308a2ea3,0x30b12fbb,0x330631c6,0x325c3185,0x34cc3426,
0xb16bb24f,0xb3fcb4aa,0xaf55b08a,0xb15fb2aa,0xabbead99,0xada6b017,0x9edfa84c,0xa102aa43,0x2a052528,0x2c632783,0x2e772cbc,0x30ba2ee9,0x30fb301a,0x33523204,0x32c131dd,0x35013453,
0xb1bcb2ae,0xb428b4db,0xafc2b0ce,0xb196b2ef,0xac18adeb,0xaddfb041,0x9f44a88b,0xa134aa82,0x2a5d2573,0x2c9027cf,0x2ed62d01,0x30eb2f2f,0x31453057,0x339e3242,0x33273235,0x35373481,
0xb20eb30d,0xb452b50d,0xb017b111,0xb1cdb335,0xac50ae3e,0xae18b06a,0x9fa8a8ca,0xa166aac1,0x2ab525bf,0x2cbc280d,0x2f362d47,0x311b2f75,0x318f3094,0x33eb3280,0x338e328d,0x356d34af,
0xb25fb36d,0xb47cb540,0xb04db155,0xb204b37a,0xac89ae90,0xae51b094,0xa006a909,0xa199ab00,0x2b0d260a,0x2ce82833,0x2f952d8c,0x314b2fbb,0x31da30d1,0x341c32be,0x33f532e5,0x35a334dd,
0xb2b1b3cd,0xb4a6b572,0xb084b199,0xb23bb3c0,0xacc2aee3,0xae8ab0be,0xa039a948,0xa1cbab40,0x2b652655,0x2d142859,0x2ff52dd2,0x317c3001,0x3224310e,0x344332fc,0x342e333e,0x35da350c,
0xb303b417,0xb4d1b5a5,0xb0bab1dd,0xb273b403,0xacfbaf36,0xaec3b0e7,0xa06ba987,0xa1fdab7f,0x2bbe26a1,0x2d40287e,0x302a2e18,0x31ac3024,0x326f314b,0x3469333b,0x34633398,0x3612353a,
0xb356b448,0xb4fcb5d9,0xb0f1b221,0xb2aab426,0xad34af88,0xaefcb111,0xa09da9c6,0xa22fabbe,0x2c0b26ec,0x2d6d28a4,0x305a2e5e,0x31dd3047,0x32bb3189,0x3490337a,0x349733f2,0x364a3569,
0xb527b60d,0xb68bb7bd,0xb2e2b449,0xb453b569,0xaf36b13b,0xb081b28d,0xa262abfd,0xa3f4acfb,0x2d9928ca,0x2efc29f8,0x320e306a,0x33983185,0x34b733b9,0x35f934dd,0x36823599,0x382e3722,
0xb553b641,0xb6bab7f5,0xb31ab46d,0xb470b58e,0xaf6fb165,0xb09db2b7,0xa294ac1e,0xa413ad1b,0x2dc528f0,0x2f292a1e,0x323e308d,0x33ca31a9,0x34df33f8,0x362234fe,0x36bb35c9,0x384d3755,
0xb57eb676,0xb6e8b817,0xb352b490,0xb48db5b3,0xafa8b18f,0xb0bab2e2,0xa2c6ac3d,0xa42cad3a,0x2df22915,0x2f552a43,0x326f30b1,0x33fc31cd,0x3506341c,0x364c351f,0x36f535f9,0x386d3789,
0xb5abb6ab,0xb717b834,0xb38bb4b4,0xb4aab5d9,0xafe2b1b9,0xb0d7b30d,0xa2f9ac5d,0xa445ad5a,0x2e1e293b,0x2f822a69,0x32a130d4,0x341731f0,0x352e343c,0x36763540,0x372f3629,0x388d37bd,
0xb5d7b6e0,0xb746b851,0xb3c3b4d8,0xb4c7b5fe,0xb00eb1e3,0xb0f4b338,0xa32bac7d,0xa45fad79,0x2e4b2961,0x2faf2a8f,0x32d230f7,0x34303214,0x3556345c,0x36a03561,0x376a365a,0x38ad37f1,
0xb604b717,0xb775b86f,0xb3fcb4fc,0xb4e4b624,0xb02ab20e,0xb111b363,0xa35dac9c,0xa478ad99,0x2e772987,0x2fdb2ab5,0x3303311b,0x34493238,0x357e347c,0x36ca3582,0x37a5368b,0x38ce3813,
0xb631b74d,0xb7a5b88d,0xb41ab520,0xb501b64a,0xb047b238,0xb12eb38e,0xa38facbc,0xa491adb9,0x2ea329ac,0x30042adb,0x3335313e,0x3463325c,0x35a7349c,0x36f535a3,0x37e236bd,0x38f0382e,
0xb65eb785,0xb7d6b8ab,0xb437b545,0xb51fb670,0xb064b262,0xb14bb3b9,0xa3c2acdb,0xa4aaadd8,0x2ed029d2,0x301a2b00,0x33663162,0x347c3280,0x35d034bd,0x372035c5,0x380f36ef,0x39113849,
0xb803b8ca,0xb8d0b9d0,0xb53cb697,0xb62db7d4,0xb168b3e4,0xb252b4a1,0xa4c3adf8,0xa58caef6,0x30312b26,0x30e42c2b,0x349532a4,0x356433c6,0x374c35e7,0x385a36fc,0x39343865,0x3a5c394d,
0xb81cb8e9,0xb8ebb9f3,0xb55ab6bd,0xb64cb7fd,0xb185b408,0xb26fb4b7,0xa4dcae18,0xa5a5af16,0x30472b4c,0x30fb2c3d,0x34af32c8,0x357e33eb,0x37773609,0x38723720,0x39573880,0x3a84396b,
0xb835b909,0xb906ba17,0xb577b6e4,0xb66bb813,0xb1a2b41e,0xb28db4ce,0xa4f5ae37,0xa5bfaf36,0x305d2b72,0x31112c50,0x34c932ec,0x35993408,0x37a4362b,0x388a3744,0x397a389c,0x3aad398a,
0xb84eb929,0xb922ba3b,0xb595b70b,0xb68ab828,0xb1c0b433,0xb2aab4e4,0xa50fae57,0xa5d8af55,0x30742b98,0x31282c63,0x34e23310,0x35b3341a,0x37d0364d,0x38a23768,0x399e38b9,0x3ad739aa,
0xb868b949,0xb93eba60,0xb5b3b733,0xb6a9b83d,0xb1ddb449,0xb2c8b4fa,0xa528ae77,0xa5f1af75,0x308a2bbe,0x313e2c76,0x34fc3335,0x35ce342d,0x37fd3670,0x38ba378c,0x39c338d6,0x3b0239ca,
0xb881b96a,0xb95aba86,0xb5d2b75b,0xb6c8b852,0xb1fab45f,0xb2e5b511,0xa541ae97,0xa60aaf95,0x30a12be3,0x31552c89,0x35163359,0x35e9343f,0x38153693,0x38d237b1,0x39e838f3,0x3b2d39eb,
0xb89bb98c,0xb977baac,0xb5f0b783,0xb6e8b868,0xb217b475,0xb303b527,0xa55aaeb6,0xa623afb5,0x30b72c05,0x316b2c9c,0x3530337d,0x36043452,0x382c36b6,0x38eb37d6,0x3a0e3910,0x3b593a0c,
0xb8b6b9ae,0xb994bad3,0xb60eb7ab,0xb708b87d,0xb235b48b,0xb321b53e,0xa573aed6,0xa63cafd5,0x30ce2c18,0x31822caf,0x354a33a2,0x361e3464,0x384336d9,0x390437fb,0x3a35392e,0x3b873a2d,
0x214d2216,0x319b326c,0x1f762084,0x2fe830c8,0x1c521de4,0x2c962e40,0x14b6197f,0x250229d7,0x97db8e48,0xa82c9ead,0x9d1b9b12,0xad6bab82,0xa0209ead,0xb05eaf14,0xa1b2a0e9,0xb204b131,
0x27f32890,0x3241332b,0x259826c6,0x306a3156,0x227b246b,0x2d202efb,0x1b122020,0x25982a87,0x9de494b6,0xa8aa9f76,0xa3a8a14d,0xae0eac32,0xa62fa502,0xb0e1afe8,0xa845a75d,0xb2b6b1cc,
0x2aa02b9b,0x32e733e8,0x28aa29a5,0x30e131e5,0x2566275d,0x2daa2fb6,0x1de422df,0x262f2b36,0xa0e997db,0xa927a020,0xa661a46b,0xaeb0aca2,0xa927a82c,0xb163b05e,0xab1daa22,0xb368b266,
0x2ca22d52,0x338d3452,0x2a872be6,0x31563273,0x278f2927,0x2e333039,0x202024cf,0x26c62be6,0xa2df997f,0xa9a5a084,0xa877a62f,0xaf53ad13,0xab36a9d7,0xb1e5b0c8,0xacfaac4b,0xb40cb300,
0x2df52ed6,0x341834b0,0x2c322d13,0x31cc3300,0x28dc2aa0,0x2ebd3096,0x214d262f,0x275d2c4b,0xa46b9b12,0xaa22a0e9,0xa9bea7f3,0xaff5ad84,0xaca2ab82,0xb266b131,0xae65ad84,0xb464b399,
0x2f46302c,0x346a350c,0x2d202e33,0x3241338d,0x29f02c0c,0x2f4630f3,0x227b278f,0x27f32ca2,0xa5669c52,0xaaa0a14d,0xab04a8dc,0xb04badf5,0xadaaac96,0xb2e7b19b,0xafcfaebd,0xb4bcb418,
0x304b30ed,0x34bc3568,0x2e0e2f53,0x32b6340c,0x2b042cc8,0x2fcf3150,0x23a82877,0x28452cfa,0xa6619d1b,0xab1da1b2,0xac25a9be,0xb09cae65,0xaeb0ad6b,0xb368b204,0xb09caff5,0xb512b464,
0x30f331ad,0x350c35c4,0x2efb3039,0x332b3452,0x2c0c2d84,0x302c31ad,0x246b2927,0x28902d52,0xa75d9de4,0xab9ba216,0xacc8aaa0,0xb0edaed6,0xafb6ae40,0xb3e8b26c,0xb150b096,0xb568b4b0,
0x355d361e,0x37c63867,0x339f3497,0x359836b4,0x3071320a,0x32913473,0x28dc2daa,0x2b363032,0xac0ca27b,0xae01a4cf,0xb13eaf46,0xb3bdb163,0xb434b2d5,0xb627b506,0xb5beb4fa,0xb826b73e,
0x35ac3678,0x3808388f,0x340934dd,0x35cf36f5,0x30b53266,0x32d534a0,0x29272e01,0x2b82305e,0xac4ba2df,0xae40a502,0xb18eafb6,0xb406b19b,0xb473b33d,0xb663b539,0xb612b545,0xb84cb784,
0x35fb36d0,0x382c38b7,0x34433521,0x36073736,0x30f932c2,0x331834ce,0x29722e59,0x2bcd308a,0xac89a344,0xae7ea534,0xb1dfb013,0xb42eb1d2,0xb4b3b3a5,0xb6a0b56b,0xb666b58f,0xb872b7c9,
0x36493728,0x385038de,0x347c3565,0x363e3776,0x313e331e,0x335c34fa,0x29be2eb0,0x2c0c30b5,0xacc8a3a8,0xaebda566,0xb22fb04b,0xb455b20a,0xb4f1b406,0xb6dcb59d,0xb6b9b5d8,0xb898b807,
0x3697377e,0x38743904,0x34b635a9,0x367537b6,0x3182337a,0x339f3527,0x2a092f08,0x2c3230e1,0xad07a406,0xaefba598,0xb27fb083,0xb47cb241,0xb530b43a,0xb717b5cf,0xb70cb621,0xb8bdb828,
0x36e437d4,0x3897392a,0x34ee35ed,0x36ab37f5,0x31c633d6,0x33e23554,0x2a542f5f,0x2c57310c,0xad45a439,0xaf3aa5cb,0xb2cfb0bb,0xb4a4b279,0xb56eb46d,0xb752b601,0xb75db669,0xb8e1b84a,
0x37303814,0x38b9394e,0x3527362f,0x36e1381a,0x320a3418,0x34123580,0x2aa02fb6,0x2c7d3137,0xad84a46b,0xaf78a5fd,0xb31eb0f3,0xb4cbb2b0,0xb5acb4a0,0xb78cb632,0xb7adb6b1,0xb905b86b,
0x377c383e,0x38db3972,0x355f3672,0x37173838,0x324e3446,0x343435ac,0x2aeb3007,0x2ca23163,0xadc3a49d,0xafb6a62f,0xb36eb12b,0xb4f1b2e7,0xb5eab4d4,0xb7c6b663,0xb7fdb6f8,0xb928b88b,
0x38fd3996,0x39f33a91,0x374c3857,0x3874393e,0x345535d8,0x355d3730,0x2cc8318e,0x2df532e7,0xaff5a661,0xb0f3a7f3,0xb518b31e,0xb649b46a,0xb800b694,0xb8dbb808,0xb94bb8ab,0xba45b99b,
0x391e39b8,0x3a0f3aad,0x37813875,0x388c3959,0x34763604,0x357d375a,0x2cee31b9,0x2e1a3312,0xb01aa694,0xb112a813,0xb53fb356,0xb66fb485,0xb81cb6c5,0xb8f5b81f,0xb96db8cb,0xba61b9b7,
0x393e39da,0x3a2b3ac7,0x37b63893,0x38a53974,0x3497362f,0x359d3784,0x2d1331e5,0x2e40333d,0xb039a6c6,0xb131a82c,0xb565b38d,0xb694b4a0,0xb838b6f5,0xb90fb836,0xb98eb8ea,0xba7cb9d2,
0x395e39fb,0x3a453ae0,0x37ea38b0,0x38bd398e,0x34b9365b,0x35be37ad,0x2d393210,0x2e653368,0xb058a6f8,0xb150a845,0xb58cb3c3,0xb6b9b4bc,0xb854b725,0xb928b84c,0xb9aeb909,0xba97b9ed,
0x397d3a1b,0x3a5f3af9,0x380f38cd,0x38d539a8,0x34da3686,0x35de37d7,0x2d5e323b,0x2e8b3393,0xb077a72a,0xb16fa85e,0xb5b2b3fa,0xb6deb4d7,0xb870b755,0xb941b863,0xb9ceb927,0xbab0ba07,
0x399b3a3a,0x3a793b10,0x382838ea,0x38ed39c1,0x34fa36b1,0x35fe3800,0x2d843266,0x2eb033bd,0xb096a75d,0xb18ea877,0xb5d8b418,0xb703b4f1,0xb88bb784,0xb95ab879,0xb9edb945,0xbac9ba21,
0x39b93a58,0x3a913b26,0x38423906,0x390439da,0x351b36dc,0x361e3814,0x2daa3291,0x2ed633e8,0xb0b5a78f,0xb1ada890,0xb5feb434,0xb728b50c,0xb8a6b7b3,0xb972b88f,0xba0bb962,0xbae0ba3a,
0x39d73a75,0x3aa93b3c,0x385b3922,0x391b39f2,0x353c3706,0x363e3828,0x2dcf32bc,0x2efb3409,0xb0d4a7c1,0xb1cca8aa,0xb624b44f,0xb74cb527,0xb8c1b7e2,0xb98ab8a5,0xba29b97f,0xbaf7ba52,
0x3ac03b50,0x3b5e3bcb,0x39323a0a,0x39de3ab8,0x365e383c,0x375738d7,0x2f21341f,0x302634c8,0xb1eba8c3,0xb2e1a98c,0xb770b542,0xb846b615,0xb9a2b8bb,0xba51b960,0xbb0dba6a,0xbb9cbb11,
0x3ad73b63,0x3b6e3bd6,0x39493a22,0x39f23acb,0x367d3850,0x377638ea,0x2f463434,0x303934dd,0xb20aa8dc,0xb300a9a5,0xb795b55d,0xb857b62f,0xb9b9b8d0,0xba65b974,0xbb22ba81,0xbba9bb24,
0x3aec3b75,0x3b7d3bdf,0x395f3a39,0x3a063ade,0x369d3864,0x379538fd,0x2f6c3449,0x304b34f1,0xb229a8f5,0xb31ea9be,0xb7b8b577,0xb868b649,0xb9d0b8e5,0xba79b987,0xbb36ba97,0xbbb6bb35,
0x3b013b86,0x3b8c3be7,0x39753a4f,0x3a193af0,0x36bc3878,0x37b3390f,0x2f91345e,0x305e3506,0xb247a90e,0xb33da9d7,0xb7dcb592,0xb879b663,0xb9e7b8fa,0xba8cb99a,0xbb4abaad,0xbbc2bb46,
0x3b153b96,0x3b993bee,0x398a3a65,0x3a2d3b02,0x36dc388b,0x37d13921,0x2fb63473,0x3071351b,0xb266a927,0xb35ca9f0,0xb800b5ac,0xb88ab67d,0xb9fdb90f,0xba9fb9ad,0xbb5cbac3,0xbbccbb56,
0x3b283ba5,0x3ba63bf4,0x39a03a7a,0x3a3f3b13,0x36fb389e,0x37ef3933,0x2fdc3488,0x30833530,0xb285a940,0xb37aaa09,0xb811b5c7,0xb89bb697,0xba12b924,0xbab1b9c0,0xbb6dbad7,0xbbd6bb65,
0x3b3b3bb3,0x3bb23bf9,0x39b53a8f,0x3a523b24,0x371a38b2,0x38073945,0x3001349d,0x30963545,0xb2a4a959,0xb399aa22,0xb823b5e1,0xb8abb6b1,0xba28b938,0xbac3b9d2,0xbb7ebaeb,0xbbdfbb74,
0x3b4d3bc0,0x3bbd3bfc,0x39ca3aa4,0x3a643b34,0x373938c5,0x38153957,0x301334b3,0x30a9355a,0xb2c2a972,0xb3b7aa3b,0xb834b5fb,0xb8bcb6ca,0xba3cb94c,0xbad4b9e4,0xbb8dbaff,0xbbe6bb82,
0x20e921b2,0x31313204,0x1ead2020,0x2f14305e,0x1b121d1b,0x2b822d6b,0xe4817db,0x1ead282c,0x997f94b6,0xa9d7a502,0x9de49c52,0xae40ac96,0xa0849f76,0xb0c8afe8,0xa216a14d,0xb26cb19b,
0x275d2845,0x31cc32b6,0x2502262f,0x2fe830e1,0x214d23a8,0x2c322e0e,0x14b61de4,0x1f7628aa,0xa0209b12,0xaa87a598,0xa46ba27b,0xaefbad20,0xa6c6a598,0xb156b06a,0xa890a7f3,0xb32bb241,
0x2a222b1d,0x32663368,0x282c2927,0x305e3163,0x246b2661,0x2ca22eb0,0x17db20e9,0x20202927,0xa2df9de4,0xab36a62f,0xa75da566,0xafb6adaa,0xa9a5a8aa,0xb1e5b0e1,0xab9baaa0,0xb3e8b2e7,
0x2c4b2cfa,0x3300340c,0x29d72b36,0x30c831e5,0x262f2877,0x2d132f53,0x197f22df,0x208429a5,0xa4cfa020,0xabe6a6c6,0xa927a78f,0xb039ae33,0xabe6aa87,0xb273b156,0xad52aca2,0xb452b38d,
0x2d842e65,0x33993464,0x2b822ca2,0x31313266,0x27f329be,0x2d842ff5,0x1b12246b,0x20e92a22,0xa62fa14d,0xac4ba75d,0xaaa0a8dc,0xb096aebd,0xad13ac32,0xb300b1cc,0xaed6adf5,0xb4b0b418,
0x2ebd2fcf,0x341834bc,0x2c962daa,0x319b32e7,0x28dc2b04,0x2df5304b,0x1c522566,0x214d2aa0,0xa78fa27b,0xaca2a7f3,0xac0ca9f0,0xb0f3af46,0xae33ad20,0xb38db241,0xb02caf46,0xb50cb46a,
0x2ff5309c,0x34643512,0x2d6b2eb0,0x32043368,0x29be2c25,0x2e65309c,0x1d1b2661,0x21b22b1d,0xa877a3a8,0xacfaa845,0xacc8ab04,0xb150afcf,0xaf53ae0e,0xb40cb2b6,0xb0edb04b,0xb568b4bc,
0x30963150,0x34b03568,0x2e402fb6,0x326c33e8,0x2aa02cc8,0x2ed630ed,0x1de4275d,0x22162b9b,0xa927a46b,0xad52a890,0xad84ac0c,0xb1adb02c,0xb039aefb,0xb452b32b,0xb1adb0f3,0xb5c4b50c,
0x34fa35be,0x373e3826,0x32d53434,0x35063627,0x2f46313e,0x316333bd,0x227b2c0c,0x24cf2e01,0xadaaa8dc,0xb032ab36,0xb20ab071,0xb473b291,0xb497b39f,0xb6b4b598,0xb61eb55d,0xb867b7c6,
0x35453612,0x3784384c,0x333d3473,0x35393663,0x2fb6318e,0x319b3406,0x22df2c4b,0x25022e40,0xae01a927,0xb05eab82,0xb266b0b5,0xb4a0b2d5,0xb4ddb409,0xb6f5b5cf,0xb678b5ac,0xb88fb808,
0x358f3666,0x37c93872,0x33a534b3,0x356b36a0,0x301331df,0x31d2342e,0x23442c89,0x25342e7e,0xae59a972,0xb08aabcd,0xb2c2b0f9,0xb4ceb318,0xb521b443,0xb736b607,0xb6d0b5fb,0xb8b7b82c,
0x35d836b9,0x38073898,0x340634f1,0x359d36dc,0x304b322f,0x320a3455,0x23a82cc8,0x25662ebd,0xaeb0a9be,0xb0b5ac0c,0xb31eb13e,0xb4fab35c,0xb565b47c,0xb776b63e,0xb728b649,0xb8deb850,
0x3621370c,0x382838bd,0x343a3530,0x35cf3717,0x3083327f,0x3241347c,0x24062d07,0x25982efb,0xaf08aa09,0xb0e1ac32,0xb37ab182,0xb527b39f,0xb5a9b4b6,0xb7b6b675,0xb77eb697,0xb904b874,
0x3669375d,0x384a38e1,0x346d356e,0x36013752,0x30bb32cf,0x327934a4,0x24392d45,0x25cb2f3a,0xaf5faa54,0xb10cac57,0xb3d6b1c6,0xb554b3e2,0xb5edb4ee,0xb7f5b6ab,0xb7d4b6e4,0xb92ab897,
0x36b137ad,0x386b3905,0x34a035ac,0x3632378c,0x30f3331e,0x32b034cb,0x246b2d84,0x25fd2f78,0xafb6aaa0,0xb137ac7d,0xb418b20a,0xb580b412,0xb62fb527,0xb81ab6e1,0xb814b730,0xb94eb8b9,
0x36f837fd,0x388b3928,0x34d435ea,0x366337c6,0x312b336e,0x32e734f1,0x249d2dc3,0x262f2fb6,0xb007aaeb,0xb163aca2,0xb446b24e,0xb5acb434,0xb672b55f,0xb838b717,0xb83eb77c,0xb972b8db,
0x38ab394b,0x399b3a45,0x36943800,0x380838db,0x331e3518,0x346a3649,0x26612ff5,0x27f330f3,0xb18eacc8,0xb2e7adf5,0xb5d8b455,0xb730b55d,0xb857b74c,0xb93eb874,0xb996b8fd,0xba91b9f3,
0x38cb396d,0x39b73a61,0x36c5381c,0x381f38f5,0x3356353f,0x3485366f,0x2694301a,0x28133112,0xb1b9acee,0xb312ae1a,0xb604b476,0xb75ab57d,0xb875b781,0xb959b88c,0xb9b8b91e,0xbaadba0f,
0x38ea398e,0x39d23a7c,0x36f53838,0x3836390f,0x338d3565,0x34a03694,0x26c63039,0x282c3131,0xb1e5ad13,0xb33dae40,0xb62fb497,0xb784b59d,0xb893b7b6,0xb974b8a5,0xb9dab93e,0xbac7ba2b,
0x390939ae,0x39ed3a97,0x37253854,0x384c3928,0x33c3358c,0x34bc36b9,0x26f83058,0x28453150,0xb210ad39,0xb368ae65,0xb65bb4b9,0xb7adb5be,0xb8b0b7ea,0xb98eb8bd,0xb9fbb95e,0xbae0ba45,
0x392739ce,0x3a073ab0,0x37553870,0x38633941,0x33fa35b2,0x34d736de,0x272a3077,0x285e316f,0xb23bad5e,0xb393ae8b,0xb686b4da,0xb7d7b5de,0xb8cdb80f,0xb9a8b8d5,0xba1bb97d,0xbaf9ba5f,
0x394539ed,0x3a213ac9,0x3784388b,0x3879395a,0x341835d8,0x34f13703,0x275d3096,0x2877318e,0xb266ad84,0xb3bdaeb0,0xb6b1b4fa,0xb800b5fe,0xb8eab828,0xb9c1b8ed,0xba3ab99b,0xbb10ba79,
0x39623a0b,0x3a3a3ae0,0x37b338a6,0x388f3972,0x343435fe,0x350c3728,0x278f30b5,0x289031ad,0xb291adaa,0xb3e8aed6,0xb6dcb51b,0xb814b61e,0xb906b842,0xb9dab904,0xba58b9b9,0xbb26ba91,
0x397f3a29,0x3a523af7,0x37e238c1,0x38a5398a,0x344f3624,0x3527374c,0x27c130d4,0x28aa31cc,0xb2bcadcf,0xb409aefb,0xb706b53c,0xb828b63e,0xb922b85b,0xb9f2b91b,0xba75b9d7,0xbb3cbaa9,
0x3a6a3b0d,0x3b113b9c,0x38bb39a2,0x39603a51,0x35423770,0x36153846,0x28c331eb,0x298c32e1,0xb41faf21,0xb4c8b026,0xb83cb65e,0xb8d7b757,0xba0ab932,0xbab8b9de,0xbb50bac0,0xbbcbbb5e,
0x3a813b22,0x3b243ba9,0x38d039b9,0x39743a65,0x355d3795,0x362f3857,0x28dc320a,0x29a53300,0xb434af46,0xb4ddb039,0xb850b67d,0xb8eab776,0xba22b949,0xbacbb9f2,0xbb63bad7,0xbbd6bb6e,
0x3a973b36,0x3b353bb6,0x38e539d0,0x39873a79,0x357737b8,0x36493868,0x28f53229,0x29be331e,0xb449af6c,0xb4f1b04b,0xb864b69d,0xb8fdb795,0xba39b95f,0xbadeba06,0xbb75baec,0xbbdfbb7d,
0x3aad3b4a,0x3b463bc2,0x38fa39e7,0x399a3a8c,0x359237dc,0x36633879,0x290e3247,0x29d7333d,0xb45eaf91,0xb506b05e,0xb878b6bc,0xb90fb7b3,0xba4fb975,0xbaf0ba19,0xbb86bb01,0xbbe7bb8c,
0x3ac33b5c,0x3b563bcc,0x390f39fd,0x39ad3a9f,0x35ac3800,0x367d388a,0x29273266,0x29f0335c,0xb473afb6,0xb51bb071,0xb88bb6dc,0xb921b7d1,0xba65b98a,0xbb02ba2d,0xbb96bb15,0xbbeebb99,
0x3ad73b6d,0x3b653bd6,0x39243a12,0x39c03ab1,0x35c73811,0x3697389b,0x29403285,0x2a09337a,0xb488afdc,0xb530b083,0xb89eb6fb,0xb933b7ef,0xba7ab9a0,0xbb13ba3f,0xbba5bb28,0xbbf4bba6,
0x3aeb3b7e,0x3b743bdf,0x39383a28,0x39d23ac3,0x35e13823,0x36b138ab,0x295932a4,0x2a223399,0xb49db001,0xb545b096,0xb8b2b71a,0xb945b807,0xba8fb9b5,0xbb24ba52,0xbbb3bb3b,0xbbf9bbb2,
0x3aff3b8d,0x3b823be6,0x394c3a3c,0x39e43ad4,0x35fb3834,0x36ca38bc,0x297232c2,0x2a3b33b7,0xb4b3b013,0xb55ab0a9,0xb8c5b739,0xb957b815,0xbaa4b9ca,0xbb34ba64,0xbbc0bb4d,0xbbfcbbbd,
0x39b839ba,0x3a973ab5,0x39b339b5,0x3a583a78,0x39af39b1,0x3a153a37,0x39aa39ad,0x39cd39f2,0x39a639a8,0x398239a8,0x39a139a4,0x3933395b,0x399d399f,0x38e03909,0x3999399b,0x388938b5,
0xb979b972,0xb865b832,0xb986b980,0xb8c7b896,0xb994b98d,0xb924b8f6,0xb9a1b99b,0xb97db951,0xb9afb9a8,0xb9d2b9a8,0xb9bcb9b5,0xba21b9fa,0xb9c9b9c3,0xba6bba47,0xb9d6b9d0,0xbab0ba8e,
0xb9f4b9fe,0xbac7bae9,0xb9dfb9e9,0xba7ebaa3,0xb9c9b9d4,0xba2dba56,0xb9b3b9be,0xb9d6ba02,0xb99db9a8,0xb979b9a8,0xb986b992,0xb916b948,0xb970b97b,0xb8adb8e2,0xb958b964,0xb840b877,
0x39373927,0x381a37b7,0x39583948,0x38943858,0x39793969,0x390738ce,0x39993989,0x3974393e,0x39b839a8,0x39da39a8,0x39d639c7,0x3a393a0b,0x39f439e5,0x3a903a65,0x3a113a02,0x3ade3ab8,
0x3a2d3a3f,0x3af43b1a,0x3a093a1b,0x3aa23acc,0x39e339f6,0x3a453a74,0x39bc39d0,0x39df3a13,0x399439a8,0x397039a8,0x396b3980,0x38f83935,0x39413956,0x387a38ba,0x3916392b,0x37e83838,
0xb8f3b8d8,0xb79bb705,0xb929b90e,0xb85fb817,0xb95db943,0xb8eab8a6,0xb990b976,0xb96bb92b,0xb9c0b9a8,0xb9e3b9a8,0xb9f0b9d8,0xba50ba1b,0xba1dba07,0xbab3ba83,0xba49ba33,0xbb0abae0,
0xba64ba7c,0xbb1ebb46,0xba31ba4b,0xbac4baf3,0xb9fcba17,0xba5cba92,0xb9c5b9e1,0xb9e7ba23,0xb98bb9a8,0xb966b9a8,0xb94fb96d,0xb8dbb922,0xb911b930,0xb845b891,0xb8d1b8f1,0xb74eb7ee,
0x38ad3887,0x36ff364e,0x38f838d3,0x382a37ac,0x3941391d,0x38cc387c,0x39863964,0x39623918,0x39c939a8,0x39eb39a8,0x3a0939e9,0x3a673a2b,0x3a453a27,0x3ad53aa0,0x3a7e3a62,0x3b323b05,
0x3b453b6e,0x3bbc3bdd,0x3ae53b17,0x3b573b8f,0x3a733aae,0x3ac73b14,0x39f03a33,0x3a113a71,0x395d39a8,0x393739a8,0x38bc390e,0x384038bf,0x380f3867,0x365f3775,0x36af376a,0x341a3540,
0xb65fb593,0xb389b115,0xb7e8b726,0xb625b4f9,0xb8adb852,0xb830b748,0xb958b905,0xb933b8b5,0xb9f4b9a8,0xba15b9a8,0xba7eba3b,0xbad1ba78,0xbaf4babc,0xbb63bb20,0xbb57bb28,0xbbc6bb9b,
0xbb68bb91,0xbbd0bbed,0xbb04bb39,0xbb6fbba6,0xba89bac9,0xbadbbb2b,0xb9f8ba43,0xba19ba7f,0xb954b9a8,0xb92eb9a8,0xb89eb8fb,0xb820b8ab,0xb7b2b83d,0xb5ebb71b,0xb60eb6e3,0xb2deb4b1,
0x35bc34d5,0x32322f0e,0x377a369e,0x35b13469,0x388e3828,0x380f36ee,0x394f38f1,0x392938a0,0x39fc39a8,0x3a1d39a8,0x3a933a4b,0x3ae53a87,0x3b133ad6,0x3b7a3b36,0x3b783b49,0x3bd93bb1,
0x3b873baf,0x3be13bf8,0x3b213b58,0x3b853bbb,0x3a9e3ae3,0x3aee3b41,0x3a003a52,0x3a213a8e,0x394a39a8,0x392439a8,0x387f38e7,0x37fe3896,0x37423812,0x357636c1,0x356a3659,0x31853420,
0xb517b414,0xb0d7abd9,0xb70ab614,0xb53ab3ae,0xb86fb7f9,0xb7ddb693,0xb946b8dd,0xb91fb88c,0xba04b9a8,0xba25b9a8,0xbaa9ba5a,0xbaf7ba95,0xbb2fbaf0,0xbb90bb4b,0xbb96bb67,0xbbe8bbc4,
0xbba3bbc9,0xbbefbbff,0xbb3dbb74,0xbb9abbcd,0xbab3bafc,0xbb01bb55,0xba09ba62,0xba29ba9c,0xb941b9a8,0xb91bb9a8,0xb85fb8d3,0xb7bdb881,0xb6d2b7cd,0xb4ffb665,0xb4c3b5ce,0xb029b31b,
0x346f32a1,0x2ef52248,0x36993587,0x34c33288,0x385037a1,0x379b3637,0x393c38c9,0x39163877,0x3a0d39a8,0x3a2d39a8,0x3abd3a69,0x3b0a3aa3,0x3b4a3b08,0x3ba33b5f,0x3bb03b82,0x3bf43bd5,
0x3bf83c00,0x3bf93bd4,0x3bac3bdc,0x3be43bfe,0x3b133b69,0x3b543bab,0x3a313aaa,0x3a503ae0,0x391139a8,0x38ea39a8,0x377a386d,0x366b3817,0x34873608,0x313b348d,0x2d9731f4,0xad65291b,
0xac3828b6,0x2ec33365,0xb44bb160,0xb0bea57f,0xb759b5da,0xb648b45d,0xb90cb862,0xb8e5b80d,0xba35b9a8,0xba54b9a8,0xbb1bbab1,0xbb5cbae6,0xbbb5bb72,0xbbe9bbb2,0xbbfcbbe3,0xbbf5bc00,
0xbbfebbfc,0xbbefbbbc,0xbbbdbbe9,0xbbeebc00,0xbb24bb7b,0xbb63bbb9,0xba39bab8,0xba58baed,0xb907b9a8,0xb8e0b9a8,0xb737b858,0xb625b802,0xb40eb5ab,0xb042b42c,0xa9b1b0cb,0x30109a48,
0x25e4ad7e,0xb0beb475,0x33a23036,0x2f8ba3db,0x3715357c,0x360233f7,0x3902384d,0x38db37ee,0x3a3d39a8,0x3a5c39a8,0x3b2c3abf,0x3b6a3af3,0x3bc53b84,0x3bf23bc0,0x3bff3bee,0x3be93c00,
0x3c003bf4,0x3be23ba0,0x3bcc3bf3,0x3bf53bff,0x3b353b8c,0x3b713bc6,0x3a413ac6,0x3a603af9,0x38fd39a8,0x38d639a8,0x36f43842,0x35df37d8,0x3328354c,0x2e913396,0x16482f40,0xb16ca852,
0x251b304e,0x32193534,0xb2adae14,0xad972aac,0xb6d2b51d,0xb5bcb334,0xb8f8b838,0xb8d1b7c2,0xba45b9a8,0xba64b9a8,0xbb3dbacc,0xbb78baff,0xbbd3bb95,0xbbf8bbcb,0xbc00bbf7,0xbbdabbfd,
0xbbfebbe6,0xbbd2bb80,0xbbd9bbfa,0xbbfbbbfb,0xbb45bb9d,0xbb7fbbd1,0xba49bad3,0xba67bb05,0xb8f3b9a8,0xb8ccb9a8,0xb6afb82d,0xb599b7ac,0xb232b4ed,0xac9cb2d2,0x294dace7,0x32c62c83,
0xac06b1db,0xb371b5f1,0x31b62b75,0x2b43adb0,0x368d34bd,0x3576326f,0x38ee3822,0x38c73796,0x3a4d39a8,0x3a6b39a8,0x3b4c3ad9,0x3b853b0b,0x3bdf3ba4,0x3bfd3bd6,0x3bfc3bfd,0x3bc83bf8,
0x3bbd3b5a,0x3b473a99,0x3bfe3bf4,0x3bf93bbe,0x3b8b3bdb,0x3bb83bf7,0x3a6f3b11,0x3a8c3b3e,0x38c139a8,0x389939a8,0x35523780,0x343236cc,0x294d320d,0xad332de2,0xb40eaedc,0xb6a4b408,
0x346336aa,0x36f438b0,0xa6ad3004,0x2e2d3451,0xb52fb1aa,0xb40ead1a,0xb8bcb76a,0xb894b6b5,0xba73b9a8,0xba90b9a8,0xbb92bb17,0xbbbdbb43,0xbbffbbe0,0xbbf6bbf9,0xbbb2bbf0,0xbb35bbb4,
0xbba5bb30,0xbb21ba5e,0xbc00bbeb,0xbbf3bbaa,0xbb98bbe4,0xbbc2bbfb,0xba76bb1d,0xba93bb49,0xb8b7b9a8,0xb88eb9a8,0xb50bb753,0xb3d3b69e,0xa17fb147,0x2f27ac51,0x34b73099,0x37423499,
0xb50bb75e,0xb790b900,0x9cb6b12e,0xb010b4e1,0x34e730e4,0x33892b11,0x38b2373d,0x38893687,0x3a7a39a8,0x3a9739a8,0x3b9e3b22,0x3bc63b4e,0x3c003be8,0x3bef3bfd,0x3b983be5,0x3b0d3b9e,
0x3b893b02,0x3af73a1f,0x3c003bdf,0x3beb3b93,0x3ba33bec,0x3bcb3bfe,0x3a7e3b28,0x3a9b3b53,0x38ad39a8,0x388439a8,0x34c33726,0x33403670,0xa51b3080,0xb08d297f,0xb55eb1c3,0xb7ddb529,
0x35b13807,0x3815394d,0x28843257,0x31093570,0xb49fb01d,0xb2f7a7da,0xb8a8b710,0xb87fb659,0xba81b9a8,0xba9eb9a8,0xbba9bb2e,0xbbcfbb58,0xbbffbbef,0xbbe6bbff,0xbb7abbd7,0xbae1bb86,
0xbb6abad0,0xbacbb9dc,0xbbfdbbd0,0xbbe1bb79,0xbbaebbf2,0xbbd3bc00,0xba85bb33,0xbaa2bb5d,0xb8a3b9a8,0xb87ab9a8,0xb47bb6f9,0xb2adb642,0x2a7aaf72,0x3185a4b6,0x360232ea,0x383a35b6,
0xb654b85d,0xb85fb996,0xac38b37d,0xb201b5fd,0x34572eaa,0x32631e48,0x389e36e3,0x3874362b,0x3a8939a8,0x3aa539a8,0x3bb33b39,0x3bd73b62,0x3bfc3bf5,0x3bdc3c00,0x3b593bc7,0x3ab33b6b,
0x39b739b9,0x3a883aa6,0x39b239b4,0x3a483a68,0x39ae39b0,0x3a033a26,0x39a939ab,0x39bb39e0,0x39a539a7,0x396e3995,0x39a039a3,0x391e3947,0x399c399e,0x38ca38f5,0x3997399a,0x3873389f,
0xb97cb975,0xb87eb84c,0xb98ab983,0xb8deb8ae,0xb997b991,0xb93bb90d,0xb9a5b99e,0xb993b967,0xb9b2b9ab,0xb9e6b9bd,0xb9bfb9b9,0xba34ba0e,0xb9ccb9c6,0xba7dba59,0xb9d9b9d3,0xbac0ba9f,
0xb9efb9f9,0xbab6bad9,0xb9d9b9e4,0xba6aba91,0xb9c4b9cf,0xba18ba42,0xb9aeb9b9,0xb9bfb9ec,0xb997b9a3,0xb961b991,0xb981b98c,0xb8fcb92f,0xb96ab975,0xb892b8c8,0xb953b95e,0xb824b85c,
0x3940392f,0x383937f6,0x39613950,0x38b13876,0x39813971,0x392338eb,0x39a03991,0x398e395a,0x39bf39b0,0x39f339c1,0x39de39cf,0x3a4f3a22,0x39fb39ec,0x3aa43a7b,0x3a183a0a,0x3af03acb,
0x3a243a36,0x3ae13b07,0x39ff3a12,0x3a8b3ab7,0x39d939ec,0x3a2c3a5d,0x39b239c6,0x39c439f9,0x398a399e,0x3953398c,0x39613975,0x38d93917,0x3936394b,0x3859389a,0x390b3921,0x37a43816,
0xb901b8e6,0xb7e6b750,0xb936b91c,0xb883b83c,0xb96ab950,0xb90bb8c8,0xb99cb983,0xb98ab94b,0xb9ccb9b4,0xb9ffb9c6,0xb9fbb9e4,0xba6aba36,0xba28ba12,0xbacaba9b,0xba53ba3e,0xbb1dbaf5,
0xba57ba70,0xbb09bb33,0xba24ba3e,0xbaabbadc,0xb9efba0a,0xba40ba77,0xb9b7b9d3,0xb9c8ba05,0xb97cb99a,0xb944b988,0xb940b95e,0xb8b6b8fe,0xb901b921,0xb81eb86b,0xb8c0b8e1,0xb6fcb79e,
0x38c0389a,0x375636a7,0x390b38e6,0x38543800,0x3953392f,0x38f238a4,0x39973975,0x3985393d,0x39d939b9,0x3a0c39ca,0x3a1839f9,0x3a843a4a,0x3a533a36,0x3aed3abb,0x3a8b3a70,0x3b473b1c,
0x3b2e3b5a,0x3ba63bce,0x3aca3afe,0x3b373b74,0x3a533a91,0x3a9d3aef,0x39cc3a12,0x39de3a42,0x39363983,0x38fc3971,0x389238e6,0x37fb3880,0x37c5383c,0x35d136eb,0x3651370d,0x330934ae,
0xb6c3b5fa,0xb460b251,0xb824b788,0xb6b8b590,0xb8d9b880,0xb873b7d5,0xb981b92f,0xb96eb8f5,0xba18b9cf,0xba48b9e0,0xba9dba5d,0xbafabaa6,0xbb0fbad9,0xbb80bb43,0xbb6cbb40,0xbbd8bbb2,
0xbb51bb7d,0xbbbdbbe0,0xbae7bb1f,0xbb4ebb8c,0xba66baa9,0xbaafbb04,0xb9d1ba1e,0xb9e2ba4e,0xb928b97e,0xb8edb96c,0xb86eb8cd,0xb7afb866,0xb74bb80b,0xb54fb684,0xb5a2b679,0xb197b411,
0x362e3549,0x338330de,0x37e6370d,0x3651350e,0x38c0385c,0x38593788,0x397c3921,0x396a38e6,0x3a2439d3,0x3a5339e4,0x3ab63a70,0x3b0f3ab7,0x3b2e3af5,0x3b973b5a,0x3b8d3b61,0x3be83bc7,
0x3b703b9c,0x3bd03bef,0x3b033b3d,0x3b653ba2,0x3a793ac1,0x3ac03b19,0x39d53a2a,0x39e63a59,0x3919397a,0x38de3967,0x384938b4,0x3761384c,0x36cf37b4,0x34cc361d,0x34f035e2,0x302332e4,
0xb596b496,0xb244aecf,0xb783b690,0xb5e8b48a,0xb8a7b836,0xb83eb73a,0xb978b912,0xb965b8d7,0xba30b9d7,0xba5fb9e8,0xbacdba82,0xbb23bac8,0xbb4cbb10,0xbbacbb6f,0xbbaabb7f,0xbbf4bbd8,
0xbb8dbbb7,0xbbe0bbf9,0xbb1dbb5a,0xbb7abbb5,0xba8bbad9,0xbad0bb2d,0xb9d9ba36,0xb9eaba65,0xb90bb975,0xb8cfb963,0xb824b89a,0xb713b831,0xb651b750,0xb447b5b3,0xb43bb549,0xad58b1a4,
0x34fc33c0,0x31032bc0,0x371e3611,0x357e3405,0x388d3811,0x382436eb,0x39733903,0x396138c8,0x3a3c39db,0x3a6a39ec,0x3ae43a94,0x3b373ad9,0x3b673b2a,0x3bbe3b83,0x3bc33b9a,0x3bfc3be7,
0x3bed3bff,0x3bff3bea,0x3b8d3bc7,0x3bcc3bf5,0x3ae13b40,0x3b1d3b83,0x39ef3a70,0x39ff3a9b,0x38c0395e,0x3883394b,0x36c33816,0x357e3750,0x33833549,0x2e84332e,0x28cf3061,0xb0aca5b2,
0xaf7ea376,0x29663166,0xb514b2fd,0xb2bfad71,0xb809b69b,0xb734b555,0xb95cb8b9,0xb949b87b,0xba75b9f1,0xbaa1ba01,0xbb49bae9,0xbb8bbb25,0xbbcfbb96,0xbbf9bbd2,0xbc00bbf2,0xbbe3bbfe,
0xbbf6bc00,0xbbfcbbda,0xbb9fbbd6,0xbbd8bbfb,0xbaf0bb52,0xbb2cbb92,0xb9f3ba7b,0xba03baa6,0xb8b1b95a,0xb873b947,0xb673b7f6,0xb52cb718,0xb276b4de,0xac5eb251,0x2052ae39,0x321f2bf2,
0x2cf4a806,0xad3fb2d8,0x34a831ee,0x31e22a93,0x37db364b,0x36fc3502,0x395738a9,0x3944386b,0x3a8039f5,0x3aab3a05,0x3b5b3af8,0x3b993b33,0x3bdd3ba7,0x3bfd3bdd,0x3bff3bfa,0x3bd13bf9,
0x3bfd3bfd,0x3bf53bc6,0x3baf3be3,0x3be23bff,0x3b003b64,0x3b393ba0,0x39f73a86,0x3a083ab0,0x38a23955,0x38633942,0x362237bf,0x34d836e0,0x31663472,0x286b3172,0xaaf82b5c,0xb390ae84,
0xa8cf2cf4,0x2fc93423,0xb43bb0de,0xb103a484,0xb7a4b5fa,0xb6c3b4ae,0xb953b89a,0xb940b85c,0xba8bb9f9,0xbab6ba0a,0xbb6cbb07,0xbba6bb40,0xbbe8bbb7,0xbc00bbe7,0xbbfabbff,0xbbbabbf1,
0xbc00bbf6,0xbbebbbae,0xbbbebbed,0xbbebbc00,0xbb0fbb74,0xbb47bbad,0xb9fbba91,0xba0cbabb,0xb892b950,0xb854b93d,0xb5d1b788,0xb484b6a7,0xb055b405,0x9248b093,0x2e6ba484,0x347e3086,
0x98b6afe2,0xb128b4d8,0x339c2f97,0x3023a420,0x376c35a8,0x368a345a,0x394e388b,0x393b384c,0x3a9639fd,0x3ac03a0e,0x3b7c3b16,0x3bb33b4d,0x3bf23bc5,0x3c003bef,0x3bf03c00,0x3ba03be5,
0x3bde3b91,0x3b8a3af7,0x3bf23bff,0x3c003be3,0x3b533bb9,0x3b823bdf,0x3a103ac5,0x3a203aec,0x38443939,0x38033925,0x342f366d,0x31b03584,0xa8392f65,0xb15a1d7f,0xb531b1c9,0xb7e0b55b,
0x3269358a,0x35a83819,0xae842a61,0x205231e2,0xb651b405,0xb567b15a,0xb936b83c,0xb923b7f6,0xbacaba12,0xbaf0ba22,0xbbbebb5a,0xbbe3bb88,0xbbfdbbf5,0xbbddbc00,0xbb81bbd6,0xbadfbb7c,
0xbbcebb70,0xbb6dbac6,0xbbf8bbfb,0xbbffbbd6,0xbb60bbc4,0xbb8dbbe7,0xba14bacf,0xba24baf5,0xb834b934,0xb7e6b921,0xb3b4b634,0xb103b549,0x2c44ada3,0x326925b2,0x35e23309,0x384135f4,
0xb3a8b63a,0xb63fb869,0x2cc2ad58,0xa89db2f0,0x3617335f,0x352c30ac,0x3931382c,0x391e37d5,0x3ad43a16,0x3afa3a26,0x3bc93b66,0x3bea3b92,0x3bf93bfa,0x3bcf3bff,0x3b5f3bc5,0x3aad3b5d,
0x3bba3b4c,0x3b4d3a93,0x3bfc3bf6,0x3bfd3bc7,0x3b6c3bce,0x3b973bed,0x3a183ad9,0x3a283afe,0x3824392f,0x37c5391c,0x330935fa,0x3055350e,0xae6b2bc0,0xb377aa61,0xb690b423,0xb890b68a,
0x347236e5,0x36d438b6,0xa9fd2f7e,0x2c1233fd,0xb5dcb2b3,0xb4f0affb,0xb92db81c,0xb919b7b4,0xbaddba1a,0xbb03ba2a,0xbbd3bb72,0xbbf0bb9c,0xbbf2bbfe,0xbbbfbbfc,0xbb38bbaf,0xba77bb3c,
0xbba4bb23,0xbb2aba5b,0xbbffbbee,0xbbfabbb6,0xbb77bbd7,0xbba1bbf3,0xba1cbae2,0xba2cbb07,0xb813b92a,0xb7a4b917,0xb25db5bf,0xaf4cb4d2,0x3048a839,0x34412cf4,0x373a34c0,0x38dc371e,
0xb50eb78e,0xb767b901,0x24e9b0d1,0xadd5b484,0x35a23207,0x34b42e9d,0x3928380b,0x39143793,0x3ae73a1e,0x3b0c3a2e,0x3bdb3b7d,0x3bf53ba6,0x3be93c00,0x3bad3bf7,0x3b0d3b97,0x3a3e3b18,
0xb999b996,0xb889b85d,0xb99db99b,0xb8e0b8b5,0xb9a1b99f,0xb933b909,0xb9a6b9a4,0xb982b95b,0xb9aab9a8,0xb9cdb9a8,0xb9afb9ad,0xba15b9f2,0xb9b3b9b1,0xba58ba37,0xb9b8b9b5,0xba97ba78,
0xb9d6b9dc,0xbab0bad0,0xb9c9b9d0,0xba6bba8e,0xb9bcb9c3,0xba21ba47,0xb9afb9b5,0xb9d2b9fa,0xb9a1b9a8,0xb97db9a8,0xb994b99b,0xb924b951,0xb986b98d,0xb8c7b8f6,0xb979b980,0xb865b896,
0x3958394d,0x38403807,0x39703964,0x38ad3877,0x3986397b,0x391638e2,0x399d3992,0x39793948,0x39b339a8,0x39d639a8,0x39c939be,0x3a2d3a02,0x39df39d4,0x3a7e3a56,0x39f439e9,0x3ac73aa3,
0x3a113a1f,0x3ade3b02,0x39f43a02,0x3a903ab8,0x39d639e5,0x3a393a65,0x39b839c7,0x39da3a0b,0x399939a8,0x397439a8,0x39793989,0x3907393e,0x39583969,0x389438ce,0x39373948,0x381a3858,
0xb916b900,0xb7e8b75e,0xb941b92b,0xb87ab838,0xb96bb956,0xb8f8b8ba,0xb994b980,0xb970b935,0xb9bcb9a8,0xb9dfb9a8,0xb9e3b9d0,0xba45ba13,0xba09b9f6,0xbaa2ba74,0xba2dba1b,0xbaf4bacc,
0xba49ba5e,0xbb0abb30,0xba1dba33,0xbab3bae0,0xb9f0ba07,0xba50ba83,0xb9c0b9d8,0xb9e3ba1b,0xb990b9a8,0xb96bb9a8,0xb95db976,0xb8eab92b,0xb929b943,0xb85fb8a6,0xb8f3b90e,0xb79bb817,
0x38d138b0,0x374e36aa,0x391138f1,0x384537ee,0x394f3930,0x38db3891,0x398b396d,0x39663922,0x39c539a8,0x39e739a8,0x39fc39e1,0x3a5c3a23,0x3a313a17,0x3ac43a92,0x3a643a4b,0x3b1e3af3,
0x3a7e3a99,0x3b323b5a,0x3a453a62,0x3ad53b05,0x3a093a27,0x3a673aa0,0x39c939e9,0x39eb3a2b,0x398639a8,0x396239a8,0x39413964,0x38cc3918,0x38f8391d,0x382a387c,0x38ad38d3,0x36ff37ac,
0xb6afb5f1,0xb41ab1db,0xb80fb76a,0xb65fb540,0xb8bcb867,0xb840b775,0xb95db90e,0xb937b8bf,0xb9f0b9a8,0xba11b9a8,0xba73ba33,0xbac7ba71,0xbae5baae,0xbb57bb14,0xbb45bb17,0xbbbcbb8f,
0xbb57bb80,0xbbc6bbe6,0xbaf4bb28,0xbb63bb9b,0xba7ebabc,0xbad1bb20,0xb9f4ba3b,0xba15ba78,0xb958b9a8,0xb933b9a8,0xb8adb905,0xb830b8b5,0xb7e8b852,0xb625b748,0xb65fb726,0xb389b4f9,
0x360e3534,0x32de304e,0x37b236e3,0x35eb34b1,0x389e383d,0x3820371b,0x395438fb,0x392e38ab,0x39f839a8,0x3a1939a8,0x3a893a43,0x3adb3a7f,0x3b043ac9,0x3b6f3b2b,0x3b683b39,0x3bd03ba6,
0x3b783ba0,0x3bd93bf4,0x3b133b49,0x3b7a3bb1,0x3a933ad6,0x3ae53b36,0x39fc3a4b,0x3a1d3a87,0x394f39a8,0x392939a8,0x388e38f1,0x380f38a0,0x377a3828,0x35b136ee,0x35bc369e,0x32323469,
0xb56ab475,0xb185ad7e,0xb742b659,0xb576b420,0xb87fb812,0xb7feb6c1,0xb94ab8e7,0xb924b896,0xba00b9a8,0xba21b9a8,0xba9eba52,0xbaeeba8e,0xbb21bae3,0xbb85bb41,0xbb87bb58,0xbbe1bbbb,
0xbb96bbbc,0xbbe8bbfc,0xbb2fbb67,0xbb90bbc4,0xbaa9baf0,0xbaf7bb4b,0xba04ba5a,0xba25ba95,0xb946b9a8,0xb91fb9a8,0xb86fb8dd,0xb7ddb88c,0xb70ab7f9,0xb53ab693,0xb517b614,0xb0d7b3ae,
0x34c33365,0x302928b6,0x36d235ce,0x34ff331b,0x385f37cd,0x37bd3665,0x394138d3,0x391b3881,0x3a0939a8,0x3a2939a8,0x3ab33a62,0x3b013a9c,0x3b3d3afc,0x3b9a3b55,0x3ba33b74,0x3bef3bcd,
0x3bb03bd4,0x3bf43c00,0x3b4a3b82,0x3ba33bd5,0x3abd3b08,0x3b0a3b5f,0x3a0d3a69,0x3a2d3aa3,0x393c39a8,0x391639a8,0x385038c9,0x379b3877,0x369937a1,0x34c33637,0x346f3587,0x2ef53288,
0xad972248,0x2d6532a1,0xb487b1f4,0xb13ba91b,0xb77ab608,0xb66bb48d,0xb911b86d,0xb8eab817,0xba31b9a8,0xba50b9a8,0xbb13baaa,0xbb54bae0,0xbbacbb69,0xbbe4bbab,0xbbf8bbdc,0xbbf9bbfe,
0xbbfcbbff,0xbbf5bbc9,0xbbb5bbe3,0xbbe9bc00,0xbb1bbb72,0xbb5cbbb2,0xba35bab1,0xba54bae6,0xb90cb9a8,0xb8e5b9a8,0xb759b862,0xb648b80d,0xb44bb5da,0xb0beb45d,0xac38b160,0x2ec3a57f,
0x29b1abd9,0xb010b414,0x340e30cb,0x30421a48,0x373735ab,0x3625342c,0x39073858,0x38e03802,0x3a3939a8,0x3a5839a8,0x3b243ab8,0x3b633aed,0x3bbd3b7b,0x3bee3bb9,0x3bfe3be9,0x3bef3c00,
0x3bff3bf8,0x3be93baf,0x3bc53bee,0x3bf23c00,0x3b2c3b84,0x3b6a3bc0,0x3a3d3abf,0x3a5c3af3,0x390239a8,0x38db39a8,0x3715384d,0x360237ee,0x33a2357c,0x2f8b33f7,0x25e43036,0xb0bea3db,
0x96482f0e,0x316c34d5,0xb328af40,0xae912852,0xb6f4b54c,0xb5dfb396,0xb8fdb842,0xb8d6b7d8,0xba41b9a8,0xba60b9a8,0xbb35bac6,0xbb71baf9,0xbbccbb8c,0xbbf5bbc6,0xbc00bbf3,0xbbe2bbff,
0xbc00bbed,0xbbdabb91,0xbbd3bbf7,0xbbf8bbfd,0xbb3dbb95,0xbb78bbcb,0xba45bacc,0xba64baff,0xb8f8b9a8,0xb8d1b9a8,0xb6d2b838,0xb5bcb7c2,0xb2adb51d,0xad97b334,0x251bae14,0x32192aac,
0xa94db115,0xb2c6b593,0x32322ce7,0x2c9cac83,0x36af34ed,0x359932d2,0x38f3382d,0x38cc37ac,0x3a4939a8,0x3a6739a8,0x3b453ad3,0x3b7f3b05,0x3bd93b9d,0x3bfb3bd1,0x3bfe3bfa,0x3bd23bfb,
0x3bfc3bdd,0x3bc83b6e,0x3bdf3bfd,0x3bfd3bf8,0x3b4c3ba4,0x3b853bd6,0x3a4d3ad9,0x3a6b3b0b,0x38ee39a8,0x38c739a8,0x368d3822,0x35763796,0x31b634bd,0x2b43326f,0xac062b75,0xb371adb0,
0x340e364e,0x36a43887,0xa94d2edc,0x2d333408,0xb552b20d,0xb432ade2,0xb8c1b780,0xb899b6cc,0xba6fb9a8,0xba8cb9a8,0xbb8bbb11,0xbbb8bb3e,0xbbfebbdb,0xbbf9bbf7,0xbbbdbbf4,0xbb47bbbe,
0xbbb2bb46,0xbb35ba7c,0xbbffbbf0,0xbbf6bbb4,0xbb92bbe0,0xbbbdbbf9,0xba73bb17,0xba90bb43,0xb8bcb9a8,0xb894b9a8,0xb52fb76a,0xb40eb6b5,0xa6adb1aa,0x2e2dad1a,0x34633004,0x36f43451,
0xb4b7b705,0xb742b8d8,0x217fb099,0xaf27b499,0x350b3147,0x33d32c51,0x38b73753,0x388e369e,0x3a7639a8,0x3a9339a8,0x3b983b1d,0x3bc23b49,0x3c003be4,0x3bf33bfb,0x3ba53beb,0x3b213baa,
0x3b983b1a,0x3b0d3a3f,0x3c003be5,0x3bef3b9e,0x3b9e3be8,0x3bc63bfd,0x3a7a3b22,0x3a973b4e,0x38b239a8,0x388939a8,0x34e7373d,0x33893687,0x9cb630e4,0xb0102b11,0xb50bb12e,0xb790b4e1,
0x355e37b7,0x37dd3927,0x251b31c3,0x308d3529,0xb4c3b080,0xb340a97f,0xb8adb726,0xb884b670,0xba7eb9a8,0xba9bb9a8,0xbba3bb28,0xbbcbbb53,0xbc00bbec,0xbbebbbfe,0xbb89bbdf,0xbaf7bb93,
0xbb7abae9,0xbae1b9fe,0xbbffbbd7,0xbbe6bb86,0xbba9bbef,0xbbcfbbff,0xba81bb2e,0xba9ebb58,0xb8a8b9a8,0xb87fb9a8,0xb49fb710,0xb2f7b659,0x2884b01d,0x3109a7da,0x35b13257,0x38153570,
0xb602b832,0xb83ab972,0xaa7ab2ea,0xb185b5b6,0x347b2f72,0x32ad24b6,0x38a336f9,0x387a3642,0x3a8539a8,0x3aa239a8,0x3bae3b33,0x3bd33b5d,0x3bfd3bf2,0x3be13c00,0x3b6a3bd0,0x3acb3b79,
0x3b593ab5,0x3ab339ba,0x3bfc3bc7,0x3bdc3b6b,0x3bb33bf5,0x3bd73c00,0x3a893b39,0x3aa53b62,0x389e39a8,0x387439a8,0x345736e3,0x3263362b,0xac382eaa,0xb2011e48,0xb654b37d,0xb85fb5fd,
0xb99ab997,0xb89fb873,0xb99eb99c,0xb8f5b8ca,0xb9a3b9a0,0xb947b91e,0xb9a7b9a5,0xb995b96e,0xb9abb9a9,0xb9e0b9bb,0xb9b0b9ae,0xba26ba03,0xb9b4b9b2,0xba68ba48,0xb9b9b9b7,0xbaa6ba88,
0xb9d3b9d9,0xba9fbac0,0xb9c6b9cc,0xba59ba7d,0xb9b9b9bf,0xba0eba34,0xb9abb9b2,0xb9bdb9e6,0xb99eb9a5,0xb967b993,0xb991b997,0xb90db93b,0xb983b98a,0xb8aeb8de,0xb975b97c,0xb84cb87e,
0x395e3953,0x385c3824,0x3975396a,0x38c83892,0x398c3981,0x392f38fc,0x39a33997,0x39913961,0x39b939ae,0x39ec39bf,0x39cf39c4,0x3a423a18,0x39e439d9,0x3a913a6a,0x39f939ef,0x3ad93ab6,
0x3a0a3a18,0x3acb3af0,0x39ec39fb,0x3a7b3aa4,0x39cf39de,0x3a223a4f,0x39b039bf,0x39c139f3,0x399139a0,0x395a398e,0x39713981,0x38eb3923,0x39503961,0x387638b1,0x392f3940,0x37f63839,
0xb921b90b,0xb816b7a4,0xb94bb936,0xb89ab859,0xb975b961,0xb917b8d9,0xb99eb98a,0xb98cb953,0xb9c6b9b2,0xb9f9b9c4,0xb9ecb9d9,0xba5dba2c,0xba12b9ff,0xbab7ba8b,0xba36ba24,0xbb07bae1,
0xba3eba53,0xbaf5bb1d,0xba12ba28,0xba9bbaca,0xb9e4b9fb,0xba36ba6a,0xb9b4b9cc,0xb9c6b9ff,0xb983b99c,0xb94bb98a,0xb950b96a,0xb8c8b90b,0xb91cb936,0xb83cb883,0xb8e6b901,0xb750b7e6,
0x38e138c0,0x379e36fc,0x39213901,0x386b381e,0x395e3940,0x38fe38b6,0x399a397c,0x39883944,0x39d339b7,0x3a0539c8,0x3a0a39ef,0x3a773a40,0x3a3e3a24,0x3adc3aab,0x3a703a57,0x3b333b09,
0x3a703a8b,0x3b1c3b47,0x3a363a53,0x3abb3aed,0x39f93a18,0x3a4a3a84,0x39b939d9,0x39ca3a0c,0x39753997,0x393d3985,0x392f3953,0x38a438f2,0x38e6390b,0x38003854,0x389a38c0,0x36a73756,
0xb70db651,0xb4aeb309,0xb83cb7c5,0xb6ebb5d1,0xb8e6b892,0xb880b7fb,0xb983b936,0xb971b8fc,0xba12b9cc,0xba42b9de,0xba91ba53,0xbaefba9d,0xbafebaca,0xbb74bb37,0xbb5abb2e,0xbbcebba6,
0xbb40bb6c,0xbbb2bbd8,0xbad9bb0f,0xbb43bb80,0xba5dba9d,0xbaa6bafa,0xb9cfba18,0xb9e0ba48,0xb92fb981,0xb8f5b96e,0xb880b8d9,0xb7d5b873,0xb788b824,0xb590b6b8,0xb5fab6c3,0xb251b460,
0x367935a2,0x34113197,0x380b374b,0x3684354f,0x38cd386e,0x386637af,0x397e3928,0x396c38ed,0x3a1e39d1,0x3a4e39e2,0x3aa93a66,0x3b043aaf,0x3b1f3ae7,0x3b8c3b4e,0x3b7d3b51,0x3be03bbd,
0x3b613b8d,0x3bc73be8,0x3af53b2e,0x3b5a3b97,0x3a703ab6,0x3ab73b0f,0x39d33a24,0x39e43a53,0x3921397c,0x38e6396a,0x385c38c0,0x37883859,0x370d37e6,0x350e3651,0x3549362e,0x30de3383,
0xb5e2b4f0,0xb2e4b023,0xb7b4b6cf,0xb61db4cc,0xb8b4b849,0xb84cb761,0xb97ab919,0xb967b8de,0xba2ab9d5,0xba59b9e6,0xbac1ba79,0xbb19bac0,0xbb3dbb03,0xbba2bb65,0xbb9cbb70,0xbbefbbd0,
0xbb7fbbaa,0xbbd8bbf4,0xbb10bb4c,0xbb6fbbac,0xba82bacd,0xbac8bb23,0xb9d7ba30,0xb9e8ba5f,0xb912b978,0xb8d7b965,0xb836b8a7,0xb73ab83e,0xb690b783,0xb48ab5e8,0xb496b596,0xaecfb244,
0x3549343b,0x31a42d58,0x37503651,0x35b33447,0x389a3824,0x38313713,0x3975390b,0x396338cf,0x3a3639d9,0x3a6539ea,0x3ad93a8b,0x3b2d3ad0,0x3b5a3b1d,0x3bb53b7a,0x3bb73b8d,0x3bf93be0,
0x3b9a3bc3,0x3be73bfc,0x3b2a3b67,0x3b833bbe,0x3a943ae4,0x3ad93b37,0x39db3a3c,0x39ec3a6a,0x39033973,0x38c83961,0x3811388d,0x36eb3824,0x3611371e,0x3405357e,0x33c034fc,0x2bc03103,
0xb061a8cf,0x25b230ac,0xb549b383,0xb32eae84,0xb816b6c3,0xb750b57e,0xb95eb8c0,0xb94bb883,0xba70b9ef,0xba9bb9ff,0xbb40bae1,0xbb83bb1d,0xbbc7bb8d,0xbbf5bbcc,0xbbffbbed,0xbbeabbff,
0xbbf2bc00,0xbbfebbe3,0xbb96bbcf,0xbbd2bbf9,0xbae9bb49,0xbb25bb8b,0xb9f1ba75,0xba01baa1,0xb8b9b95c,0xb87bb949,0xb69bb809,0xb555b734,0xb2fdb514,0xad71b2bf,0xa376af7e,0x31662966,
0x2e39a052,0xabf2b21f,0x34de3276,0x32512c5e,0x37f63673,0x3718352c,0x395a38b1,0x39473873,0x3a7b39f3,0x3aa63a03,0x3b523af0,0x3b923b2c,0x3bd63b9f,0x3bfb3bd8,0x3c003bf6,0x3bda3bfc,
0x3bfa3bff,0x3bf93bd1,0x3ba73bdd,0x3bdd3bfd,0x3af83b5b,0x3b333b99,0x39f53a80,0x3a053aab,0x38a93957,0x386b3944,0x364b37db,0x350236fc,0x31ee34a8,0x2a9331e2,0xa8062cf4,0xb2d8ad3f,
0xab5c2af8,0x2e843390,0xb472b166,0xb172a86b,0xb7bfb622,0xb6e0b4d8,0xb955b8a2,0xb942b863,0xba86b9f7,0xbab0ba08,0xbb64bb00,0xbba0bb39,0xbbe3bbaf,0xbbffbbe2,0xbbfdbbfd,0xbbc6bbf5,
0xbbffbbfa,0xbbf1bbba,0xbbb7bbe8,0xbbe7bc00,0xbb07bb6c,0xbb40bba6,0xb9f9ba8b,0xba0abab6,0xb89ab953,0xb85cb940,0xb5fab7a4,0xb4aeb6c3,0xb0deb43b,0xa484b103,0x2cf4a8cf,0x34232fc9,
0x2484ae6b,0xb086b47e,0x34053055,0x30931248,0x378835d1,0x36a73484,0x39503892,0x393d3854,0x3a9139fb,0x3abb3a0c,0x3b743b0f,0x3bad3b47,0x3bed3bbe,0x3c003beb,0x3bf63c00,0x3bae3beb,
0x3c003bf0,0x3be53ba0,0x3bc53bf2,0x3bef3c00,0x3b163b7c,0x3b4d3bb3,0x39fd3a96,0x3a0e3ac0,0x388b394e,0x384c393b,0x35a8376c,0x345a368a,0x2f97339c,0xa4203023,0xafe298b6,0xb4d8b128,
0x31c93531,0x355b37e0,0xaf652839,0x9d7f315a,0xb66db42f,0xb584b1b0,0xb939b844,0xb925b803,0xbac5ba10,0xbaecba20,0xbbb9bb53,0xbbdfbb82,0xbbffbbf2,0xbbe3bc00,0xbb91bbde,0xbaf7bb8a,
0xbbd6bb81,0xbb7cbadf,0xbbf5bbfd,0xbc00bbdd,0xbb5abbbe,0xbb88bbe3,0xba12baca,0xba22baf0,0xb83cb936,0xb7f6b923,0xb405b651,0xb15ab567,0x2a61ae84,0x31e22052,0x358a3269,0x381935a8,
0xb309b5e2,0xb5f4b841,0x2da3ac44,0xa5b2b269,0x363433b4,0x35493103,0x39343834,0x392137e6,0x3acf3a14,0x3af53a24,0x3bc43b60,0x3be73b8d,0x3bfb3bf8,0x3bd63bff,0x3b703bce,0x3ac63b6d,
0x3bc53b5f,0x3b5d3aad,0x3bfa3bf9,0x3bff3bcf,0x3b663bc9,0x3b923bea,0x3a163ad4,0x3a263afa,0x382c3931,0x37d5391e,0x335f3617,0x30ac352c,0xad582cc2,0xb2f0a89d,0xb63ab3a8,0xb869b63f,
0x34233690,0x368a3890,0xabc02e6b,0x2a613377,0xb5fab309,0xb50eb055,0xb92fb824,0xb91cb7c5,0xbad9ba18,0xbafeba28,0xbbcebb6c,0xbbedbb97,0xbbf6bbfc,0xbbc7bbfd,0xbb4cbbba,0xba93bb4d,
0xbbafbb38,0xbb3cba77,0xbbfebbf2,0xbbfcbbbf,0xbb72bbd3,0xbb9cbbf0,0xba1abadd,0xba2abb03,0xb81cb92d,0xb7b4b919,0xb2b3b5dc,0xaffbb4f0,0x2f7ea9fd,0x33fd2c12,0x36e53472,0x38b636d4,
0xb4c0b73a,0xb71eb8dc,0x2839b048,0xacf4b441,0x35bf325d,0x34d22f4c,0x392a3813,0x391737a4,0x3ae23a1c,0x3b073a2c,0x3bd73b77,0x3bf33ba1,0x3bee3bff,0x3bb63bfa,0x3b233ba4,0x3a5b3b2a,
0x3b973b0d,0x3b183a3e,0x3c003be9,0x3bf73bad,0x3b7d3bdb,0x3ba63bf5,0x3a1e3ae7,0x3a2e3b0c,0x380b3928,0x37933914,0x320735a2,0x2e9d34b4,0xb0d124e9,0xb484add5,0xb78eb50e,0xb901b767,
0xb97239ba,0x39dc3996,0xb8323ab5,0x3ad0385d,0x3927b9fe,0xba1fb94d,0x37b7bae9,0xbb02b807,0xb8d83a3f,0x3a5e3900,0xb7053b1a,0x3b30375e,0x3887ba7c,0xba99b8b0,0x364ebb46,0xbb5ab6aa,
0xb90039dc,0x3a3f3972,0xad7e3be6,0x3bf83115,0x3807ba99,0xbae9b887,0xabd9bc00,0xbbfca248,0xb5f13b30,0x3b6e3705,0x32a13bed,0x3bd4b04e,0x3365bba0,0xbbc9b4d5,0xb593bbaf,0xbb803475,
0xb88739fe,0x3a99394d,0x35f13bbc,0x3b6eb414,0x3593bb1a,0xbb80b75e,0xb8b0bb02,0xba7c37b7,0xaf0e3bc9,0x3bf43365,0x3a1f39dc,0x3927b972,0xb04ebc00,0xbbed2248,0xbb30b85d,0xb7053ab5,
0xb8073a1f,0x3ae93927,0x39fe3a3f,0x394db900,0x31dbbb80,0xbbddb593,0xbb6eb832,0xb5f13ad0,0x31153c00,0x3be62248,0x3bff32a1,0x28b6bbd4,0xb7b7bb91,0xbb023534,0xbba0304e,0x34d53bed,
0xb7053a3f,0x3b303900,0x3bbc375e,0x3414bb1a,0x2248bbc9,0xbc00b365,0xbbdda8b6,0x31db3bff,0x36aa3bd4,0x3b46b2a1,0x3a7cb64e,0xb8b0bb5a,0xba1fba5e,0xb92738d8,0xb7b739fe,0x3b02394d,
0xb5f13a5e,0x3b6e38d8,0x3bd42bd9,0xb2a1bbfc,0xb115bbf4,0xbbe6af0e,0xb9dc375e,0x39723b1a,0x39273b46,0x3a1fb6aa,0x3475bad0,0xbbafb832,0xbb91b887,0xb5343a99,0x34143c00,0x3bbc2248,
0xb4d53a7c,0x3ba038b0,0x3a3fb593,0xb900bb80,0xb534bc00,0xbb912248,0xb4143ab5,0x3bbc385d,0x3a993a5e,0x3887b8d8,0xb5f1bbfc,0xbb6e2bd9,0xbbffb475,0x28b63baf,0x3ad03a1f,0x3832b927,
0xb3653a99,0x3bc93887,0x36aab996,0xbb46b9ba,0xb7b7bbed,0xbb02304e,0x34d53bfc,0x3ba02bd9,0x3b913927,0x3534ba1f,0xbae9ba3f,0xb8073900,0xbb5a28b6,0x364e3bff,0x3bd43115,0xb2a1bbe6,
0xb1153ab5,0x3be6385d,0xa8b6bb6e,0xbbffb5f1,0xb900bbbc,0xba3f3414,0x3a1f3b30,0x3927b705,0x3bfc375e,0x2bd9bb1a,0xbbedb475,0x304e3baf,0xb9ba3593,0x39963b80,0x3887b832,0xba99bad0,
0xad7e3ad0,0x3bf83832,0xb7b7bbff,0xbb0228b6,0xb9febb6e,0xb94d35f1,0x3bed3887,0x304eba99,0x3bd43414,0xb2a1bbbc,0xb9963534,0x39ba3b91,0xb6aa3900,0x3b463a3f,0xb115bba0,0xbbe6b4d5,
0xa2483ae9,0x3c003807,0xba99bb30,0xb8873705,0xbad0bb02,0xb83237b7,0x3b462d7e,0xb6aabbf8,0x3b1a28b6,0xb75ebbff,0xaf0e3a7c,0x3bf438b0,0xabd93ab5,0x3bfc385d,0xba5ebb5a,0xb8d8364e,
0x2bd93b02,0x3bfc37b7,0xbbedb927,0xb04e3a1f,0xbb6eba7c,0xb5f138b0,0x385db6aa,0xbab5bb46,0x39dcb1db,0xb972bbdd,0x38323c00,0x3ad02248,0x34d53bbc,0x3ba03414,0xbbf4b705,0x2f0e3b30,
0x304e3b1a,0x3bed375e,0xbb91b475,0x35343baf,0xbbd4b9dc,0xb2a13972,0x2248ba7c,0xbc00b8b0,0x3832b64e,0xbad0bb5a,0x3b803a99,0x3593b887,0x39003bfc,0x3a3fabd9,0xb9273414,0x3a1f3bbc,
0x32a13b30,0x3bd43705,0xb996304e,0x39ba3bed,0xbbffb927,0xa8b63a1f,0xb832bbf4,0xbad0af0e,0x3475b8b0,0xbbafba7c,0x3ba03593,0xb4d5bb80,0x3ae93b6e,0x3807b5f1,0x2bd93a99,0x3bfc3887,
0x34753b46,0x3baf36aa,0xb4d53832,0x3ba03ad0,0xbbedb85d,0x304e3ab5,0xbb30bb5a,0xb705364e,0x2248b9fe,0xbc00b94d,0x3887b414,0xba99bbbc,0x3be63a1f,0x3115b927,0x39dc3bf4,0x3972af0e,
0x35933b5a,0x3b80364e,0x31153a99,0x3be63887,0xbba0b705,0x34d53b30,0xbbf4b8d8,0x2f0e3a5e,0xb414bb02,0xbbbcb7b7,0xabd9ba1f,0xbbfcb927,0x3bd43832,0xb2a1bad0,0x3c003972,0xa248b9dc,
0x36aa3b6e,0x3b4635f1,0x38b03bdd,0x3a7c31db,0xbb1ab534,0x375e3b91,0xba3fb04e,0x39003bed,0xb807bbaf,0xbae9b475,0xb94dbbf8,0xb9fead7e,0x3ab53365,0xb85dbbc9,0x39ba28b6,0xb996bbff,
0x37b73b80,0x3b023593,0x3b1a3bc9,0x375eb365,0xba5eb2a1,0x38d83bd4,0xb53435f1,0x3b913b6e,0xb9babbfc,0xb996abd9,0xbbddbae9,0xb1db3807,0x38b0ad7e,0xba7cbbf8,0x28b6b900,0xbbffba3f,
0x385d3b91,0x3ab53534,0x3c003a5e,0x2248b8d8,0xb972ad7e,0x39dc3bf8,0x33653a3f,0x3bc93900,0xbb02bbe6,0xb7b73115,0xbb1ab6aa,0x375e3b46,0x3414b64e,0xbbbcbb5a,0xb94dbbdd,0xb9feb1db,
0x38d83ba0,0x3a5e34d5,0x3b3037b7,0xb705bb02,0xb85d28b6,0x3ab53bff,0x39ba3be6,0x39963115,0xbbc9bb6e,0xb36535f1,0xb6aa31db,0x3b463bdd,0xaf0eb94d,0xbbf4b9fe,0xbbf8bae9,0xad7e3807,
0x394d3baf,0x39fe3475,0x38d82d7e,0xba5ebbf8,0xb64e3115,0x3b5a3be6,0x3bd43b80,0x32a1b593,0xbbffba99,0x28b63887,0x336539ba,0x3bc93996,0xb75ebae9,0xbb1ab807,0xba3fb534,0x39003b91,
0x39ba3bbc,0x39963414,0x31dbb534,0xbbddbb91,0xb3653475,0x3bc93baf,0x3b803927,0xb593ba1f,0xbba0b972,0x34d539dc,0x3a3f3be6,0x39003115,0xb9febbd4,0xb94db2a1,0xb04e35f1,0x3bed3b6e,
0x3a1f3bc9,0x39273365,0xb475b972,0xbbafb9dc,0xabd9364e,0x3bfc3b5a,0x38d831db,0xba5ebbdd,0xbab5b807,0x385d3ae9,0x3c003b30,0x2248b705,0xbb80bbf4,0xb5932f0e,0x38b03b1a,0x3a7c375e,
0x3a7c3bd4,0x38b032a1,0xb972bb5a,0xb9dcb64e,0x2f0e3807,0x3bf43ae9,0x2d7eb534,0xbbf8bb91,0xb94db4d5,0x39fe3ba0,0x3a5e37b7,0xb8d8bb02,0xbc00bb46,0x224836aa,0x3bdd3bc9,0x31dbb365,
0x3ad03bdd,0x383231db,0xbb80bc00,0xb5932248,0x347538d8,0x3baf3a5e,0xb75eb9fe,0xbb1ab94d,0xb705ad7e,0x3b303bf8,0x3414af0e,0xbbbcbbf4,0xbb6eb9dc,0x35f13972,0x3ab538b0,0xb85dba7c,
0x3b1a3be6,0x375e3115,0xbbf4bb46,0x2f0e36aa,0x37053996,0x3b3039ba,0xbae9bbd4,0xb807b2a1,0xb1db304e,0x3bdd3bed,0xb64eb94d,0xbb5ab9fe,0xb9dcb7b7,0x39723b02,0x3365ad7e,0xbbc9bbf8,
0x3b5a3bed,0x364e304e,0xbab5b94d,0x385d39fe,0x38b03a3f,0x3a7c3900,0xbbffbba0,0x28b634d5,0x2d7e3593,0x3bf83b80,0xbb02bbc9,0xb7b7b365,0xb705b1db,0x3b303bdd,0xb807b9ba,0xbae9b996,
0x3b913bf4,0x35342f0e,0xb807b4d5,0x3ae93ba0,0x39ba3ad0,0x39963832,0xba99b972,0x388739dc,0x3593385d,0x3b803ab5,0xbbe6bb6e,0x311535f1,0xad7e304e,0x3bf83bed,0xbbafbbfc,0xb475abd9,
0x3bbc3bf8,0x34142d7e,0xabd92f0e,0x3bfc3bf4,0x3a993b46,0x388736aa,0xb64eb365,0x3b5a3bc9,0x38b039ba,0x3a7c3996,0xb972b85d,0x39dc3ab5,0x34753705,0x3baf3b30,0xbb1aba5e,0x375e38d8,
0x3bdd3bfc,0x31db2bd9,0x364e3807,0x3b5a3ae9,0x3b463ba0,0x36aa34d5,0x31153475,0x3be63baf,0x3a3f3ad0,0x39003832,0xad7e28b6,0x3bf83bff,0x38d83996,0x3a5e39ba,0xb534b2a1,0x3b913bd4,
0x3bf43bff,0x2f0e28b6,0x3a1f3a7c,0x392738b0,0x3bbc3bdd,0x341431db,0x394d39ba,0x39fe3996,0x3b5a3b91,0x364e3534,0x385d38d8,0x3ab53a5e,0x3ad03b1a,0x3832375e,0x36aa37b7,0x3b463b02,
0x3bff3c00,0x28b62248,0x3bc93bd4,0x336532a1,0x3bf83bfc,0x2d7e2bd9,0x3baf3bbc,0x34753414,0x3bed3bf4,0x304e2f0e,0x3b913ba0,0x353434d5,0x3bdd3be6,0x31db3115,0x3b6e3b80,0x35f13593,
0xb5933b6e,0x3b8035f1,0xb1153bdd,0x3be631db,0x34d5bb91,0xbba0b534,0x2f0ebbed,0xbbf4b04e,0xb4143baf,0x3bbc3475,0xabd93bf8,0x3bfc2d7e,0x32a1bbc9,0xbbd4b365,0x2248bbff,0xbc00a8b6,
0x37b73b46,0x3b02b6aa,0x3b1a3832,0x375ebad0,0xb8d8bab5,0xba5e385d,0xbb91b64e,0xb5343b5a,0x39ba39fe,0x3996b94d,0x3bdd3414,0x31dbbbbc,0xba7cb927,0xb8b03a1f,0xbbffaf0e,0xa8b63bf4,
0x3bd43534,0x32a1bb91,0x39bab8d8,0xb996ba5e,0xbbffad7e,0x28b63bf8,0xb8323a3f,0x3ad03900,0x3bafb115,0xb475bbe6,0x34d5bb46,0xbba0b6aa,0xbae9364e,0x38073b5a,0xabd93bdd,0x3bfc31db,
0x3a5eb75e,0xb8d8bb1a,0xb705bbaf,0xbb303475,0xb85d39dc,0x3ab53972,0x39ba3a7c,0x3996b8b0,0x3365bb5a,0xbbc9b64e,0xbb46b887,0xb6aa3a99,0x2f0e3bfc,0x3bf42bd9,0x3bf83414,0x2d7ebbbc,
0x2bd9bbaf,0xbbfcb475,0xbbedad7e,0x304e3bf8,0x35f13be6,0x3b6eb115,0x3ab5b593,0xb85dbb80,0xb9dcba99,0xb9723887,0xb83239ba,0x3ad03996,0x3ba03807,0x34d5bae9,0x2f0ebb91,0xbbf4b534,
0xb9babae9,0xb9963807,0xb1db3b30,0x3bdd3705,0x3bc937b7,0x3365bb02,0xb593bbf8,0xbb802d7e,0xbba028b6,0x34d53bff,0x3a3f3a7c,0x3900b8b0,0x394db85d,0xb9febab5,0xbbedb64e,0xb04e3b5a,
0xbbf8b365,0x2d7e3bc9,0x3b0239dc,0x37b7b972,0x39feb64e,0xb94dbb5a,0xbbedb1db,0x304e3bdd,0xb2a13ae9,0x3bd43807,0x39bab705,0xb996bb30,0xb6aabbf4,0xbb462f0e,0xb1153b1a,0x3be6375e,
0xb8b0385d,0x3a7c3ab5,0x39dcb5f1,0xb972bb6e,0xaf0ebbbc,0xbbf4b414,0xad7e3b30,0x3bf83705,0x39fe3b1a,0x394db75e,0xb8d8bbaf,0xba5e3475,0xbc00b593,0x22483b80,0x3bdd3832,0x31dbbad0,
0x33653bdd,0x3bc931db,0xb6aabc00,0xbb462248,0xbb02ba5e,0xb7b738d8,0x3ba0394d,0x34d5b9fe,0x3b912d7e,0xb534bbf8,0xbae92f0e,0x38073bf4,0xb64e3972,0x3b5a39dc,0x32a1ba7c,0xbbd4b8b0,
0x3b1a3a7c,0x375eb8b0,0xbbf4b593,0x2f0e3b80,0xbb30a248,0x37053c00,0x3807b85d,0xbae9bab5,0x31dbba5e,0xbbddb8d8,0x364e3bfc,0x3b5a2bd9,0x39723baf,0x39dcb475,0xbbc9b927,0xb3653a1f,
0x3b6e304e,0xb5f1bbed,0xb2a139fe,0x3bd4394d,0xb1153a3f,0x3be63900,0xb9dcbba0,0xb97234d5,0xba1fbb80,0xb9273593,0x3baf3365,0xb475bbc9,0x3b9131db,0xb534bbdd,0xb41439ba,0x3bbc3996,
0x3534b900,0xbb91ba3f,0x3ae93b1a,0x3807b75e,0x39ba3bc9,0x3996b365,0xba9928b6,0x38873bff,0xbb80b2a1,0x35933bd4,0xb115bb5a,0xbbe6b64e,0x2d7eba5e,0xbbf8b8d8,0x3baf39fe,0x3475b94d,
0xb807bbf8,0xbae9ad7e,0x39feaf0e,0xb94dbbf4,0x3bdd36aa,0xb1dbbb46,0x35f13bc9,0x3b6e3365,0xb11539ba,0x3be63996,0xbbffb85d,0x28b63ab5,0xbb02bb30,0xb7b73705,0x34d5b8d8,0xbba0ba5e,
0xbbddb9fe,0xb1db394d,0xb64ebbbc,0xbb5ab414,0x36aab75e,0xbb46bb1a,0x3be637b7,0xb115bb02,0x3a3f3bc9,0x3900b365,0xad7e39dc,0x3bf83972,0xba5ea248,0x38d83c00,0xbb91bab5,0xb534385d,
0xba3fa8b6,0x39003bff,0xbbf8b8b0,0x2d7e3a7c,0xb807bbdd,0xbae9b1db,0x2bd9b9ba,0xbbfcb996,0x3b6e3534,0xb5f1bb91,0x3bd43a5e,0x32a1b8d8,0x33653b1a,0x3bc9375e,0xb59337b7,0x3b803b02,
0xa8b63996,0x3bff39ba,0xb365385d,0x3bc93ab5,0xbbf8b9fe,0xad7e394d,0xbbafbae9,0xb4753807,0x304eb900,0xbbedba3f,0x3534b75e,0xbb91bb1a,0x3bdd3a7c,0x31dbb8b0,0x3b6e3b46,0x35f1b6aa,
0x39dc3c00,0x3972a248,0x3ad03bd4,0x3832b2a1,0xb9272bd9,0x3a1f3bfc,0xb7b73414,0x3b023bbc,0xba5ebbf4,0xb8d82f0e,0xbb30bba0,0xb70534d5,0x3887b115,0xba99bbe6,0x364eb593,0xbb5abb80,
0x3bf43972,0xaf0eb9dc,0x3a1f3115,0xb927bbe6,0x34143a99,0x3bbc3887,0x39fe3c00,0x394d2248,0xbb5ab705,0x364e3b30,0xb85d304e,0x3ab53bed,0xb832bba0,0xbad0b4d5,0xbb46bbaf,0xb6aa3475,
0x3887abd9,0xba99bbfc,0xb5f1bae9,0xbb6eb807,0x3b803ba0,0x3593b4d5,0x3a7c3475,0xb8b0bbaf,0xaf0e3832,0x3bf43ad0,0x3a1f3bff,0x392728b6,0xbbedb996,0x304e39ba,0xb70532a1,0x3b303bd4,
0xb414ba1f,0xbbbcb927,0xbbfcba3f,0x2bd93900,0x3a993593,0xb887bb80,0xb64ebad0,0xbb5ab832,0x3a7c3c00,0x38b02248,0x39dc32a1,0xb972bbd4,0xb4753534,0x3baf3b91,0x3b1a3bed,0x375eb04e,
0xbb30bbf4,0xb7052f0e,0xb41434d5,0x3bbc3ba0,0x2248b832,0xbc00bad0,0xbbddb9dc,0x31db3972,0x3b46385d,0xb6aabab5,0xb8b0bb6e,0xba7cb5f1,0x3a1f3bed,0x3927304e,0x37b7abd9,0xbb02bbfc,
0xbb5ab8d8,0x364e3a5e,0x3ab53bfc,0x385d2bd9,0xba7cbbf4,0xb8b0af0e,0xa8b6375e,0x3bff3b1a,0x2d7eb6aa,0xbbf8bb46,0xbb02b832,0x37b73ad0,0x3b303887,0xb705ba99,0xbae9bc00,0xb807a248,
0xb4d53115,0x3ba03be6,0x3a3f36aa,0xb900bb46,0xbb91b996,0x353439ba,0x3bbc3bd4,0x3414b2a1,0xba99bbed,0xb887b04e,0x35f139fe,0x3b6e394d,0xa8b6b7b7,0xbbffbb02,0xb832ad7e,0x3ad03bf8,
0x38323a99,0x3ad03887,0xb593b996,0xbb80b9ba,0xb475304e,0x3baf3bed,0x375e2bd9,0xbb1abbfc,0xbb30b927,0x37053a1f,0x3bbc3a3f,0xb414b900,0xbb6ebbff,0xb5f128b6,0x3ab53be6,0x385d3115,
0x3be63bd4,0x3115b2a1,0xbbffbb5a,0x28b6364e,0x39003ae9,0x3a3f3807,0xba1fbb91,0xb927b534,0xabd934d5,0x3bfc3ba0,0xb04eb7b7,0xbbedbb02,0xb9bab6aa,0x39963b46,0x38873365,0xba99bbc9,
0x3a1f3832,0xb927bad0,0xb47528b6,0x3baf3bff,0x3bfc3b6e,0xabd9b5f1,0xba5eb887,0x38d83a99,0x3ab53bbc,0x385d3414,0xbc00bb91,0x22483534,0x35933900,0x3b803a3f,0xba7cbba0,0xb8b0b4d5,
0x2248b414,0xbc00bbbc,0x3a993b91,0x38873534,0x38323475,0xbad0bbaf,0x36aa3927,0x3b463a1f,0x3b1a39dc,0xb75eb972,0xaf0e3115,0x3bf43be6,0x3bfc3bd4,0x2bd9b2a1,0xb8d8b5f1,0x3a5e3b6e,
0xb9febb02,0xb94db7b7,0x3a5e3927,0xb8d8ba1f,0xb64eb8b0,0xbb5aba7c,0x3bd43b46,0xb2a1b6aa,0x28b6b1db,0xbbffbbdd,0x3bc93c00,0x33652248,0x375e3414,0xbb1abbbc,0x3a3f3b30,0x39003705,
0xbbedbba0,0x304e34d5,0xb534b7b7,0xbb91bb02,0xbbd4bbff,0xb2a1a8b6,0x2248b115,0xbc00bbe6,0xbad0bb6e,0xb832b5f1,0x359331db,0xbb80bbdd,0xb900b9fe,0xba3fb94d,0x39273807,0xba1fbae9,
0xb85db705,0x3ab53b30,0xbc00bbed,0x2248304e,0xb9dcb927,0x39723a1f,0xbbc9bbf4,0xb365af0e,0xbb02ba7c,0x37b738b0,0xbb1abb80,0xb75eb593,0xbbbcbb6e,0x341435f1,0xb9feba99,0xb94db887,
0x34753593,0x3baf3b80,0xb4d5b365,0x3ba03bc9,0x304e32a1,0x3bed3bd4,0xb705b5f1,0x3b303b6e,0xa2482bd9,0x3c003bfc,0xb887b807,0x3a993ae9,0xb115ad7e,0x3be63bf8,0xb972b900,0x39dc3a3f,
0x3b463b5a,0x36aa364e,0x3a7c3a99,0x38b03887,0x3b1a3b30,0x375e3705,0x3a3f3a5e,0x390038d8,0x3ae93b02,0x380737b7,0x39fe3a1f,0x394d3927,0x3ab53ad0,0x385d3832,0x39ba39dc,0x39963972,
0x28b63c00,0x3bffa248,0x33653bd4,0x3bc9b2a1,0xad7ebbfc,0xbbf82bd9,0xb475bbbc,0xbbaf3414,0x304e3bf4,0x3bedaf0e,0x35343ba0,0x3b91b4d5,0xb1dbbbe6,0xbbdd3115,0xb5f1bb80,0xbb6e3593,
0x3bf4a8b6,0xaf0ebbff,0x3a1fb8b0,0xb927ba7c,0xbbbc31db,0x34143bdd,0xb94d3996,0x39fe39ba,0x3b5ab534,0xb64ebb91,0x385dba5e,0xbab5b8d8,0xbad0375e,0x38323b1a,0xb6aa3b02,0x3b4637b7,
0xb1dbbbfc,0xbbdd2bd9,0xbb5ab807,0xb64e3ae9,0x36aa3ba0,0x3b46b4d5,0x3be63475,0x3115bbaf,0xb900bad0,0xba3f3832,0xbbf8a8b6,0x2d7e3bff,0x3a5e3996,0x38d8b9ba,0x3b91b2a1,0xb534bbd4,
0xbbbc2d7e,0x34143bf8,0x2bd93bf4,0x3bfc2f0e,0x3a99b6aa,0xb887bb46,0xb64ebbc9,0xbb5a3365,0xb8b03996,0x3a7c39ba,0x39723ab5,0x39dcb85d,0x3475bb30,0xbbafb705,0xbb1ab8d8,0xb75e3a5e,
0x35343bf4,0x3b91af0e,0x3ae9b4d5,0xb807bba0,0xb996bad0,0xb9ba3832,0xb8873972,0x3a9939dc,0x3b80385d,0x3593bab5,0x3115bb6e,0xbbe6b5f1,0xbbf8b04e,0x2d7e3bed,0x34753bfc,0x3bafabd9,
0x3b5ab04e,0xb64ebbed,0xbab5b9fe,0xb85d394d,0xb8b03900,0x3a7c3a3f,0x3bff34d5,0x28b6bba0,0x2d7ebb80,0xbbf8b593,0xbb023365,0x37b73bc9,0x37053bdd,0x3b30b1db,0x3807b996,0xbae9b9ba,
0xb75ebbe6,0xbb1a3115,0xaf0e3b46,0x3bf436aa,0x3b303996,0x3705b9ba,0xb807bbd4,0xbae932a1,0xbbddb04e,0x31db3bed,0x3b5a394d,0x364eb9fe,0x3972b7b7,0xb9dcbb02,0xbbc9ad7e,0x33653bf8,
0xbad031db,0x38323bdd,0x3b802248,0xb593bc00,0x3475ba5e,0xbbafb8d8,0xb75e394d,0x3b1a39fe,0x37053bf8,0x3b30ad7e,0xb414bbf4,0xbbbcaf0e,0xbb6eb972,0xb5f139dc,0x3ab53a7c,0x385db8b0,
0x38b03bd4,0x3a7cb2a1,0xb9dcbb5a,0xb972364e,0xbbf4b807,0xaf0e3ae9,0x3bf83534,0xad7ebb91,0x39feb4d5,0xb94dbba0,0xb8d837b7,0x3a5e3b02,0xa2483b46,0x3c0036aa,0xb1dbbbc9,0xbbddb365,
0x3a1fb365,0xb927bbc9,0xb47539dc,0x3baf3972,0x2bd93b5a,0x3bfc364e,0xb8d8bbdd,0xba5e31db,0xbab5bae9,0xb85d3807,0x3c003705,0xa248bb30,0x3b802f0e,0xb593bbf4,0xb8b0375e,0x3a7c3b1a,
0xb996bbbc,0xb9ba3414,0x3bdd3534,0xb1dbbb91,0x3bc93475,0xb365bbaf,0xb5933927,0x3b803a1f,0xb4d53972,0x3ba039dc,0xb900bbe6,0xba3f3115,0xb94dbbd4,0xb9fe32a1,0x3bed35f1,0xb04ebb6e,
0xb94d3475,0x39fe3baf,0xb8d8bbf8,0xba5e2d7e,0xb64ebbe6,0xbb5ab115,0x3bd43593,0xb2a1bb80,0x3bff3887,0x28b6ba99,0xb3653996,0x3bc939ba,0xb75e3807,0x3b1a3ae9,0xba3fbb91,0xb9003534,
0x3a5e3ba0,0x38d8b4d5,0xb70537b7,0x3b303b02,0xbab5a8b6,0x385d3bff,0xb996bbe6,0xb9ba3115,0xb365bb6e,0xbbc9b5f1,0x3b4631db,0xb6aabbdd,0x3bf4394d,0x2f0eb9fe,0x2d7e3ae9,0x3bf83807,
0x385db534,0xbab5bb91,0x3c0038d8,0xa248ba5e,0x39723bf8,0x39dcad7e,0xb3653900,0x3bc93a3f,0xbb02b115,0x37b73be6,0xbb1abb46,0xb75e36aa,0xb414bb5a,0xbbbcb64e,0x394db1db,0xb9febbdd,
0xbb02bb80,0xb7b73593,0xb75ebbc9,0xbb1ab365,0x38d8b2a1,0xba5ebbd4,0x3b9135f1,0xb534bb6e,0x39963bfc,0x39baabd9,0x31db3ae9,0x3bdd3807,0xba7cad7e,0x38b03bf8,0xbbffb900,0x28b63a3f,
0xb6aa35f1,0x3b463b6e,0xb8b031db,0x3a7c3bdd,0xbb1abb91,0xb75e3534,0xba3fbbed,0xb900304e,0x3807b475,0xbae9bbaf,0x394dad7e,0xb9febbf8,0x3ab53bc9,0x385db365,0x39ba3bff,0x3996a8b6,
0x3b803b5a,0x3593b64e,0x3be63a99,0x3115b887,0xb4d53705,0x3ba03b30,0xaf0e38d8,0x3bf43a5e,0xbbbcbb02,0xb41437b7,0xbbfcba1f,0xabd93927,0x32a1b832,0xbbd4bad0,0x2248b972,0xbc00b9dc,
0x3475b6aa,0xbbafbb46,0xb4d5bad0,0xbba0b832,0x3bed3ab5,0x304eb85d,0x3b30364e,0xb705bb5a,0x2248394d,0x3c0039fe,0x38873bbc,0x3a993414,0xbbe6b927,0x31153a1f,0xb9dcaf0e,0x39723bf4,
0xbbd4bb30,0xb2a13705,0xb9bab04e,0x39963bed,0xa8b6b927,0xbbffba1f,0xbad0bbf4,0xb8322f0e,0x3baf38b0,0xb475ba7c,0x34d5b593,0xbba0bb80,0x38073b6e,0x3ae935f1,0x3bfc3a99,0x2bd9b887,
0xb04e375e,0x3bed3b1a,0x3b913baf,0x3534b475,0xbbd4b972,0x32a139dc,0x224838b0,0x3c003a7c,0xb832bb5a,0xbad0b64e,0xbb80b887,0x35933a99,0x39002bd9,0xba3fbbfc,0xb927bbbc,0xba1fb414,
0x3bfc3b02,0x2bd9b7b7,0xb04eb927,0xbbedba1f,0x35f13a7c,0x3b6e38b0,0x3ab536aa,0xb85dbb46,0xb972b1db,0x39dc3bdd,0x3ad03c00,0x3832a248,0xbba0bbbc,0xb4d53414,0xaf0e3705,0x3bf43b30,
0xa248b807,0xbc00bae9,0xba99b705,0x38873b30,0x3ad037b7,0xb832bb02,0xbb46bbf8,0xb6aa2d7e,0x3b1a3bff,0x375ea8b6,0xaf0eb8b0,0xbbf4ba7c,0x2bd9385d,0x3bfc3ab5,0x3a5e364e,0xb8d8bb5a,
0xbbf8bad0,0x2d7e3832,0x3b023bff,0x37b728b6,0xb94dbb6e,0xb9feb5f1,0x304e3887,0x3bed3a99,0x32a1b414,0xbbd4bbbc,0xb9bab534,0x39963b91,0x3b463900,0xb6aaba3f,0xbbe6bba0,0xb11534d5,
0x3115385d,0x3be63ab5,0x28b6b5f1,0xbbffbb6e,0xb900b414,0x3a3f3bbc,0x3a1f3705,0xb927bb30,0xbbfcbb1a,0x2bd9375e,0x3bed3baf,0x304eb475,0xb9babb80,0xb996b593,0x38873ad0,0x3a993832,
0x3bc93a99,0xb365b887,0xbb46b996,0x36aa39ba,0x3b023bed,0x37b7304e,0xbba0bbfc,0xb4d52bd9,0x35343927,0x3b913a1f,0xb807ba3f,0xbae9b900,0xb64ea8b6,0x3b5a3bff,0x32a1b115,0xbbd4bbe6,
0xb4d5b8b0,0xbba0ba7c,0x3a3f3b80,0x39003593,0x35342248,0xbb91bc00,0x3414385d,0x3bbc3ab5,0x3a9938d8,0xb887ba5e,0xb5f1abd9,0x3b6e3bfc,0x3bff3baf,0x28b6b475,0xbad0b927,0x38323a1f,
0xbb6eba5e,0x35f138d8,0x32a1abd9,0xbbd4bbfc,0xbbe6bbf4,0xb1152f0e,0x3972375e,0xb9dcbb1a,0xba1fbb46,0xb927b6aa,0x3baf3ad0,0xb475b832,0xb534b887,0xbb91ba99,0x3bbc3c00,0x3414a248,
0x37053900,0x3b303a3f,0xbbbcbb1a,0x3414375e,0x22483365,0x3c003bc9,0xbbddbbff,0xb1db28b6,0xb6aab2a1,0x3b463bd4,0xba7cbb5a,0xb8b0b64e,0xba1fb8d8,0x39273a5e,0xb7b7b94d,0xbb02b9fe,
0x3ae93a1f,0xb807b927,0x394d3a3f,0x39fe3900,0x3bdd3b80,0xb1dbb593,0x35f13832,0x3b6e3ad0,0x3be63c00,0x3115a248,0x28b632a1,0x3bff3bd4,0x3b023b91,0x37b73534,0xb4d5b04e,0x3ba03bed,
0xb887b94d,0xba99b9fe,0x35f13414,0xbb6ebbbc,0xb593b75e,0xbb80bb1a,0x38b037b7,0xba7cbb02,0xaf0eb365,0xbbf4bbc9,0x3a1f3972,0xb927b9dc,0x304e2248,0xbbedbc00,0x3b303ab5,0xb705b85d,
0xba3fb9dc,0x39003972,0xbbf8bbe6,0x2d7e3115,0xbae9ba99,0x38073887,0xbbfcbc00,0xabd92248,0xbb6ebb30,0x35f13705,0xbbd4bbed,0xb2a1b04e,0xbbc9bba0,0x336534d5,0xbb80bbaf,0xb593b475,
0x39723996,0x39dc39ba,0x3832385d,0x3ad03ab5,0x3927394d,0x3a1f39fe,0x37b73807,0x3b023ae9,0x38d83900,0x3a5e3a3f,0x3705375e,0x3b303b1a,0x388738b0,0x3a993a7c,0x364e36aa,0x3b5a3b46,
0x36aa3b5a,0x3b46b64e,0x38b03a99,0x3a7cb887,0xb75ebb30,0xbb1a3705,0xb900ba5e,0xba3f38d8,0x38073b02,0x3ae9b7b7,0x394d3a1f,0x39feb927,0xb85dbad0,0xbab53832,0xb996b9dc,0xb9ba3972,
0x3475bb80,0xbbafb593,0xb4d5bbc9,0xbba03365,0xb04e3bd4,0x3bed32a1,0x37053b6e,0x3b30b5f1,0xa248bbfc,0xbc00abd9,0xb887bae9,0xba993807,0x31153bf8,0x3be6ad7e,0x39723a3f,0x39dcb900,
0xbab53705,0x385d3b30,0xa2483bed,0x3c00304e,0x3972b927,0xb9dcba1f,0xb365bbf4,0xbbc92f0e,0xb7b73a7c,0x3b0238b0,0x375e3b80,0x3b1ab593,0x3414bb6e,0xbbbcb5f1,0xb94dba99,0xb9fe3887,
0x3bed34d5,0x304ebba0,0x3534bb02,0xbb91b7b7,0xbbd428b6,0x32a13bff,0x22483be6,0x3c003115,0x3ad0b5f1,0xb832bb6e,0xb593bbdd,0xbb8031db,0xb900394d,0x3a3f39fe,0x39273ae9,0x3a1fb807,
0xb94dbb02,0xb9fe37b7,0xb8d83927,0x3a5e3a1f,0x3b5a38b0,0x364eba7c,0x32a1bb46,0xbbd4b6aa,0xbbffb1db,0x28b63bdd,0x33653c00,0x3bc9a248,0x3b1ab414,0xb75ebbbc,0xb900bb30,0xba3f3705,
0x22483bbc,0x3c003414,0x3a99b534,0xb887bb91,0xb832bbaf,0xbad03475,0xb6aa3a1f,0x3b463927,0x3b1a3972,0x375eb9dc,0xaf0ebbe6,0xbbf4b115,0xbbfcb2a1,0x2bd93bd4,0x38d83b6e,0x3a5eb5f1,
0x3927b832,0xba1fbad0,0xbbafa8b6,0x34753bff,0xabd93b6e,0x3bfc35f1,0x38d8b887,0xba5eba99,0xb85dbbbc,0xbab53414,0xa2483b91,0x3c003534,0x3b803900,0x3593ba3f,0xb8b0bba0,0xba7c34d5,
0xbbe6b2a1,0x31153bd4,0x3bff364e,0x28b6bb5a,0x3900b807,0xba3fbae9,0xba1f3534,0x39273b91,0x2bd93ba0,0x3bfc34d5,0x304ebb02,0xbbedb7b7,0xb9babb46,0xb99636aa,0x38873bc9,0x3a99b365,
0x3ad03a99,0x3832b887,0xbb80b996,0xb59339ba,0xbbafb04e,0x34753bed,0x3b1aabd9,0xb75ebbfc,0x3705b927,0xbb30ba1f,0xb4143a3f,0x3bbc3900,0x35f13bff,0x3b6e28b6,0xb85dbbe6,0xbab53115,
0xb4d5bbe6,0xbba0b115,0x3a3f3b46,0x3900b6aa,0x3b9139ba,0x3534b996,0xbbbcb2a1,0x34143bd4,0xba99304e,0x38873bed,0x35f1b94d,0xbb6eb9fe,0x28b6bb02,0xbbffb7b7,0x38323bf8,0x3ad0ad7e,
0xb64e38d8,0x3b5a3a5e,0xb85dbbfc,0xbab52bd9,0xb8b0bbf4,0xba7c2f0e,0x3bff375e,0xa8b6bb1a,0x3bf836aa,0xad7ebb46,0xb7b73832,0x3b023ad0,0xb7053887,0x3b303a99,0xb807bc00,0xbae92248,
0x3b302f0e,0xb705bbf4,0x34143ba0,0x3bbc34d5,0x22483ad0,0x3c003832,0xbbddb972,0xb1db39dc,0xbb46bab5,0xb6aa385d,0x38b0b5f1,0xba7cbb6e,0x3a1fb04e,0xb927bbed,0x37b73bfc,0x3b022bd9,
0xbbbcba1f,0xb4143927,0x2bd9ba3f,0xbbfcb900,0x3887b593,0xba99bb80,0x3b5a3ad0,0x364eb832,0x38b03c00,0x3a7ca248,0xb97232a1,0x39dc3bd4,0xbbafb534,0x34753b91,0xb75ebbed,0xbb1ab04e,
0x38873bfc,0x3a992bd9,0xb5f13807,0x3b6e3ae9,0xbb80b4d5,0x35933ba0,0xba7cbbaf,0xb8b03475,0xaf0ebad0,0xbbf4b832,0x3a1fa8b6,0xb927bbff,0x3bed39ba,0x304eb996,0x37053bd4,0x3b3032a1,
0x2f0eb972,0xbbf4b9dc,0x3927b115,0xba1fbbe6,0x3bbc3a99,0x3414b887,0x394d3c00,0x39fea248,0xb64e3705,0x3b5a3b30,0xbab5b04e,0x385d3bed,0xbad0bba0,0xb83234d5,0xb6aabbaf,0xbb46b475,
0xb9dca248,0x39723c00,0xbad0b2a1,0x38323bd4,0xb927bbfc,0xba1fabd9,0xb7b7bbbc,0xbb02b414,0x3a5e2f0e,0xb8d8bbf4,0x3b3034d5,0xb705bba0,0x38873be6,0x3a993115,0x364e3b80,0x3b5a3593,
0x3bff3996,0xa8b6b9ba,0x3bc9385d,0xb365bab5,0x2d7e39fe,0x3bf8394d,0x34753ae9,0x3baf3807,0xbbedb900,0x304e3a3f,0xbb91b75e,0x35343b1a,0xb1dbba7c,0xbbddb8b0,0xb5f1bb46,0xbb6eb6aa,
0xba3fbbff,0xb90028b6,0xbbf8ba7c,0xad7e38b0,0x3807b1db,0xbae9bbdd,0xabd9b996,0xbbfcb9ba,0x3b6e3b91,0x35f1b534,0x3bd438d8,0xb2a1ba5e,0xb365375e,0x3bc93b1a,0x35933b02,0x3b8037b7,
0x31db39fe,0x3bdd394d,0x3b5a3bbc,0x364eb414,0xbb46b75e,0x36aa3b1a,0xb11537b7,0x3be63b02,0xb900bbc9,0xba3fb365,0xbbf8b9dc,0x2d7e3972,0x38d8a248,0xba5ebc00,0xb534bab5,0xbb91b85d,
0x3807ad7e,0xbae9bbf8,0xb9febbf4,0xb94daf0e,0x3bdd3b46,0x31dbb6aa,0x35f1b365,0xbb6ebbc9,0x31153996,0x3be639ba,0x3bff3ab5,0x28b6b85d,0xbb02b705,0x37b73b30,0x34d53a5e,0x3ba038d8,
0xbb91b900,0x35343a3f,0x38073b1a,0x3ae9375e,0xb996bbc9,0xb9bab365,0xb887a8b6,0x3a993bff,0x3593b2a1,0xbb80bbd4,0xbbe6bb5a,0xb115364e,0x3bf83a5e,0xad7eb8d8,0xb475b9fe,0xbbafb94d,
0x3b6e3bed,0x35f1b04e,0xb2a1b94d,0xbbd4b9fe,0x31153900,0x3be63a3f,0x39dc34d5,0xb972bba0,0xba1fb593,0x39273b80,0x3baf3bc9,0x3475b365,0xbb91bbdd,0xb53431db,0x34143996,0x3bbc39ba,
0xb75eba7c,0xbb1ab8b0,0xaf0e3593,0x3bf43b80,0x3705a248,0xbb30bc00,0xbae9b85d,0x38073ab5,0x3bdd3a5e,0xb1dbb8d8,0xbb5abbfc,0xb64e2bd9,0x39dc3baf,0x39723475,0xb365b927,0xbbc9ba1f,
0xb36531db,0x3bc93bdd,0x36aa2248,0xbb46bc00,0xbb02b8d8,0x37b73a5e,0x3ba039fe,0xb4d5b94d,0xbb91bbf8,0xb5342d7e,0x3ae93bf4,0x38072f0e,0xb64eb9dc,0xbb5ab972,0x32a138b0,0x3bd43a7c,
0x3a7c385d,0xb8b0bab5,0xb972b5f1,0x39dc3b6e,0x3bf43bbc,0x2f0eb414,0xbbf8bb30,0x2d7e3705,0x394d3b1a,0x39fe375e,0xba5ebbaf,0xb8d8b475,0xa2483593,0x3c003b80,0xb1dbb832,0xbbddbad0,
0xbbf8bbc9,0xad7e3365,0x3b023972,0xb7b7b9dc,0xb9febb5a,0xb94db64e,0x3bed3bdd,0x304eb1db,0xb2a1b807,0xbbd4bae9,0x39ba3b30,0x39963705,0x36aa2f0e,0xbb46bbf4,0x3115375e,0x3be63b1a,
0x39963ae9,0x39ba3807,0xbbddbb30,0x31db3705,0x336537b7,0x3bc93b02,0xbb80bbf8,0xb593ad7e,0xb4d5a8b6,0x3ba03bff,0xb900ba7c,0xba3fb8b0,0xb9feb85d,0x394d3ab5,0xb04eb64e,0xbbedbb5a,
0xabd9b475,0xbbfcbbaf,0x3bed3bf8,0x304ead7e,0x35f13115,0xbb6ebbe6,0x3ab53b80,0x385d3593,0x39dc3887,0xb972ba99,0x38323996,0x3ad039ba,0x3ba03ae9,0xb4d5b807,0x2f0e3534,0x3bf43b91,
0xb8d8b75e,0x3a5e3b1a,0xbb30bbaf,0xb705b475,0xbab5b9dc,0x385d3972,0xb996ba7c,0xb9bab8b0,0xbbc9bb5a,0x3365364e,0xb6aab887,0xbb46ba99,0xbbf4bbfc,0xaf0e2bd9,0xad7eb414,0xbbf8bbbc,
0x3bd43b91,0xb2a1b534,0x39ba3a5e,0x399638d8,0x3bff3bf8,0x28b6ad7e,0x38323900,0x3ad03a3f,0x3baf3be6,0x34753115,0x34d536aa,0x3ba03b46,0x3ae93b5a,0x3807364e,0x2bd931db,0x3bfc3bdd,
0xbb02bb46,0xb7b7b6aa,0xb75eb832,0xbb1abad0,0xba5ebab5,0xb8d8b85d,0xb534b64e,0xbb91bb5a,0xb996b9fe,0xb9bab94d,0xb1dbb414,0xbbddbbbc,0xb8b0b927,0xba7cba1f,0xa8b6af0e,0xbbffbbf4,
0x359335f1,0x3b803b6e,0x311531db,0x3be63bdd,0x34d53534,0x3ba03b91,0x2f0e304e,0x3bf43bed,0x34143475,0x3bbc3baf,0x2bd92d7e,0x3bfc3bf8,0x32a13365,0x3bd43bc9,0x224828b6,0x3c003bff,
0x40000,0x60002,0xc0008,0xe000a,0x380034,0x3a0036,0x40003c,0x42003e,0x6c0068,0x6e006a,0x740070,0x760072,0xa0009c,0xa2009e,0xa800a4,0xaa00a6,
0xd400d0,0xd600d2,0xdc00d8,0xde00da,0x1080104,0x10a0106,0x110010c,0x112010e,0x13c0138,0x13e013a,0x1440140,0x1460142,0x170016c,0x172016e,0x1780174,0x17a0176,
0x1a401a0,0x1a601a2,0x1ac01a8,0x1ae01aa,0x1d801d4,0x1da01d6,0x1e001dc,0x1e201de,0x20c0208,0x20e020a,0x2140210,0x2160212,0x240023c,0x242023e,0x2480244,0x24a0246,
0x2740270,0x2760272,0x27c0278,0x27e027a,0x2a802a4,0x2aa02a6,0x2b002ac,0x2b202ae,0x2dc02d8,0x2de02da,0x2e402e0,0x2e602e2,0x310030c,0x312030e,0x3180314,0x31a0316,
0x3440340,0x3460342,0x34c0348,0x34e034a,0x3780374,0x37a0376,0x380037c,0x382037e,0x3ac03a8,0x3ae03aa,0x3b403b0,0x3b603b2,0x3e003dc,0x3e203de,0x3e803e4,0x3ea03e6,
0x4140410,0x4160412,0x41c0418,0x41e041a,0x4480444,0x44a0446,0x450044c,0x452044e,0x47c0478,0x47e047a,0x4840480,0x4860482,0x4b004ac,0x4b204ae,0x4b804b4,0x4ba04b6,
0x4e404e0,0x4e604e2,0x4ec04e8,0x4ee04ea,0x5180514,0x51a0516,0x520051c,0x522051e,0x54c0548,0x54e054a,0x5540550,0x5560552,0x580057c,0x582057e,0x5880584,0x58a0586,
0x5b405b0,0x5b605b2,0x5bc05b8,0x5be05ba,0x5e805e4,0x5ea05e6,0x5f005ec,0x5f205ee,0x61c0618,0x61e061a,0x6240620,0x6260622,0x650064c,0x652064e,0x6580654,0x65a0656,
0x140010,0x160012,0x120010,0x440012,0x480044,0x4a0046,0x460044,0x780046,0x7c0078,0x7e007a,0x7a0078,0xac007a,0xb000ac,0xb200ae,0xae00ac,0xe000ae,
0xe400e0,0xe600e2,0xe200e0,0x11400e2,0x1180114,0x11a0116,0x1160114,0x1480116,0x14c0148,0x14e014a,0x14a0148,0x17c014a,0x180017c,0x182017e,0x17e017c,0x1b0017e,
0x1b401b0,0x1b601b2,0x1b201b0,0x1e401b2,0x1e801e4,0x1ea01e6,0x1e601e4,0x21801e6,0x21c0218,0x21e021a,0x21a0218,0x24c021a,0x250024c,0x252024e,0x24e024c,0x280024e,
0x2840280,0x2860282,0x2820280,0x2b40282,0x2b802b4,0x2ba02b6,0x2b602b4,0x2e802b6,0x2ec02e8,0x2ee02ea,0x2ea02e8,0x31c02ea,0x320031c,0x322031e,0x31e031c,0x350031e,
0x3540350,0x3560352,0x3520350,0x3840352,0x3880384,0x38a0386,0x3860384,0x3b80386,0x3bc03b8,0x3be03ba,0x3ba03b8,0x3ec03ba,0x3f003ec,0x3f203ee,0x3ee03ec,0x42003ee,
0x4240420,0x4260422,0x4220420,0x4540422,0x4580454,0x45a0456,0x4560454,0x4880456,0x48c0488,0x48e048a,0x48a0488,0x4bc048a,0x4c004bc,0x4c204be,0x4be04bc,0x4f004be,
0x4f404f0,0x4f604f2,0x4f204f0,0x52404f2,0x5280524,0x52a0526,0x5260524,0x5580526,0x55c0558,0x55e055a,0x55a0558,0x58c055a,0x590058c,0x592058e,0x58e058c,0x5c0058e,
0x5c405c0,0x5c605c2,0x5c205c0,0x5f405c2,0x5f805f4,0x5fa05f6,0x5f605f4,0x62805f6,0x62c0628,0x62e062a,0x62a0628,0x65c062a,0x660065c,0x662065e,0x65e065c,0x18065e,
0x180018,0x4c001a,0x1a0018,0x4c001a,0x4c004c,0x80004e,0x4e004c,0x80004e,0x800080,0xb40082,0x820080,0xb40082,0xb400b4,0xe800b6,0xb600b4,0xe800b6,
0xe800e8,0x11c00ea,0xea00e8,0x11c00ea,0x11c011c,0x150011e,0x11e011c,0x150011e,0x1500150,0x1840152,0x1520150,0x1840152,0x1840184,0x1b80186,0x1860184,0x1b80186,
0x1b801b8,0x1ec01ba,0x1ba01b8,0x1ec01ba,0x1ec01ec,0x22001ee,0x1ee01ec,0x22001ee,0x2200220,0x2540222,0x2220220,0x2540222,0x2540254,0x2880256,0x2560254,0x2880256,
0x2880288,0x2bc028a,0x28a0288,0x2bc028a,0x2bc02bc,0x2f002be,0x2be02bc,0x2f002be,0x2f002f0,0x32402f2,0x2f202f0,0x32402f2,0x3240324,0x3580326,0x3260324,0x3580326,
0x3580358,0x38c035a,0x35a0358,0x38c035a,0x38c038c,0x3c0038e,0x38e038c,0x3c0038e,0x3c003c0,0x3f403c2,0x3c203c0,0x3f403c2,0x3f403f4,0x42803f6,0x3f603f4,0x42803f6,
0x4280428,0x45c042a,0x42a0428,0x45c042a,0x45c045c,0x490045e,0x45e045c,0x490045e,0x4900490,0x4c40492,0x4920490,0x4c40492,0x4c404c4,0x4f804c6,0x4c604c4,0x4f804c6,
0x4f804f8,0x52c04fa,0x4fa04f8,0x52c04fa,0x52c052c,0x560052e,0x52e052c,0x560052e,0x5600560,0x5940562,0x5620560,0x5940562,0x5940594,0x5c80596,0x5960594,0x5c80596,
0x5c805c8,0x5fc05ca,0x5ca05c8,0x5fc05ca,0x5fc05fc,0x63005fe,0x5fe05fc,0x63005fe,0x6300630,0x6640632,0x6320630,0x6640632,0x6640664,0x1c0666,0x6660664,0x1c0666,
0x1c001c,0x50001e,0x1e001c,0x50001e,0x500050,0x840052,0x520050,0x840052,0x840084,0xb80086,0x860084,0xb80086,0xb800b8,0xec00ba,0xba00b8,0xec00ba,
0xec00ec,0x12000ee,0xee00ec,0x12000ee,0x1200120,0x1540122,0x1220120,0x1540122,0x1540154,0x1880156,0x1560154,0x1880156,0x1880188,0x1bc018a,0x18a0188,0x1bc018a,
0x1bc01bc,0x1f001be,0x1be01bc,0x1f001be,0x1f001f0,0x22401f2,0x1f201f0,0x22401f2,0x2240224,0x2580226,0x2260224,0x2580226,0x2580258,0x28c025a,0x25a0258,0x28c025a,
0x28c028c,0x2c0028e,0x28e028c,0x2c0028e,0x2c002c0,0x2f402c2,0x2c202c0,0x2f402c2,0x2f402f4,0x32802f6,0x2f602f4,0x32802f6,0x3280328,0x35c032a,0x32a0328,0x35c032a,
0x35c035c,0x390035e,0x35e035c,0x390035e,0x3900390,0x3c40392,0x3920390,0x3c40392,0x3c403c4,0x3f803c6,0x3c603c4,0x3f803c6,0x3f803f8,0x42c03fa,0x3fa03f8,0x42c03fa,
0x42c042c,0x460042e,0x42e042c,0x460042e,0x4600460,0x4940462,0x4620460,0x4940462,0x4940494,0x4c80496,0x4960494,0x4c80496,0x4c804c8,0x4fc04ca,0x4ca04c8,0x4fc04ca,
0x4fc04fc,0x53004fe,0x4fe04fc,0x53004fe,0x5300530,0x5640532,0x5320530,0x5640532,0x5640564,0x5980566,0x5660564,0x5980566,0x5980598,0x5cc059a,0x59a0598,0x5cc059a,
0x5cc05cc,0x60005ce,0x5ce05cc,0x60005ce,0x6000600,0x6340602,0x6020600,0x6340602,0x6340634,0x6680636,0x6360634,0x6680636,0x6680668,0x20066a,0x66a0668,0x20066a,
0x5d605d6,0x60a05d6,0x5d605d6,0x60a060a,0x60a060a,0x63e063e,0x60a060a,0x63e063e,0x63e063e,0x672063e,0x63e063e,0x6720672,0x6720672,0x280028,0x6720672,0x280028,
0x5060506,0x53a0506,0x5060506,0x53a053a,0x53a053a,0x56e056e,0x53a053a,0x56e056e,0x56e056e,0x5a2056e,0x56e056e,0x5a205a2,0x5a205a2,0x5d605d6,0x5a205a2,0x5d605d6,
0x4360436,0x46a0436,0x4360436,0x46a046a,0x46a046a,0x49e049e,0x46a046a,0x49e049e,0x49e049e,0x4d2049e,0x49e049e,0x4d204d2,0x4d204d2,0x5060506,0x4d204d2,0x5060506,
0x3660366,0x39a0366,0x3660366,0x39a039a,0x39a039a,0x3ce03ce,0x39a039a,0x3ce03ce,0x3ce03ce,0x40203ce,0x3ce03ce,0x4020402,0x4020402,0x4360436,0x4020402,0x4360436,
0x2960296,0x2ca0296,0x2960296,0x2ca02ca,0x2ca02ca,0x2fe02fe,0x2ca02ca,0x2fe02fe,0x2fe02fe,0x33202fe,0x2fe02fe,0x3320332,0x3320332,0x3660366,0x3320332,0x3660366,
0x1c601c6,0x1fa01c6,0x1c601c6,0x1fa01fa,0x1fa01fa,0x22e022e,0x1fa01fa,0x22e022e,0x22e022e,0x262022e,0x22e022e,0x2620262,0x2620262,0x2960296,0x2620262,0x2960296,
0xf600f6,0x12a00f6,0xf600f6,0x12a012a,0x12a012a,0x15e015e,0x12a012a,0x15e015e,0x15e015e,0x192015e,0x15e015e,0x1920192,0x1920192,0x1c601c6,0x1920192,0x1c601c6,
0x260026,0x5a0026,0x260026,0x5a005a,0x5a005a,0x8e008e,0x5a005a,0x8e008e,0x8e008e,0xc2008e,0x8e008e,0xc200c2,0xc200c2,0xf600f6,0xc200c2,0xf600f6,
0x5d405d4,0x60805d4,0x5d405d4,0x6080608,0x6080608,0x63c063c,0x6080608,0x63c063c,0x63c063c,0x670063c,0x63c063c,0x6700670,0x6700670,0x260026,0x6700670,0x260026,
0x5040504,0x5380504,0x5040504,0x5380538,0x5380538,0x56c056c,0x5380538,0x56c056c,0x56c056c,0x5a0056c,0x56c056c,0x5a005a0,0x5a005a0,0x5d405d4,0x5a005a0,0x5d405d4,
0x4340434,0x4680434,0x4340434,0x4680468,0x4680468,0x49c049c,0x4680468,0x49c049c,0x49c049c,0x4d0049c,0x49c049c,0x4d004d0,0x4d004d0,0x5040504,0x4d004d0,0x5040504,
0x3640364,0x3980364,0x3640364,0x3980398,0x3980398,0x3cc03cc,0x3980398,0x3cc03cc,0x3cc03cc,0x40003cc,0x3cc03cc,0x4000400,0x4000400,0x4340434,0x4000400,0x4340434,
0x2940294,0x2c80294,0x2940294,0x2c802c8,0x2c802c8,0x2fc02fc,0x2c802c8,0x2fc02fc,0x2fc02fc,0x33002fc,0x2fc02fc,0x3300330,0x3300330,0x3640364,0x3300330,0x3640364,
0x1c401c4,0x1f801c4,0x1c401c4,0x1f801f8,0x1f801f8,0x22c022c,0x1f801f8,0x22c022c,0x22c022c,0x260022c,0x22c022c,0x2600260,0x2600260,0x2940294,0x2600260,0x2940294,
0xf400f4,0x12800f4,0xf400f4,0x1280128,0x1280128,0x15c015c,0x1280128,0x15c015c,0x15c015c,0x190015c,0x15c015c,0x1900190,0x1900190,0x1c401c4,0x1900190,0x1c401c4,
0x240024,0x580024,0x240024,0x580058,0x580058,0x8c008c,0x580058,0x8c008c,0x8c008c,0xc0008c,0x8c008c,0xc000c0,0xc000c0,0xf400f4,0xc000c0,0xf400f4,
0x5d205d2,0x60605d2,0x5d205d2,0x6060606,0x6060606,0x63a063a,0x6060606,0x63a063a,0x63a063a,0x66e063a,0x63a063a,0x66e066e,0x66e066e,0x240024,0x66e066e,0x240024,
0x5020502,0x5360502,0x5020502,0x5360536,0x5360536,0x56a056a,0x5360536,0x56a056a,0x56a056a,0x59e056a,0x56a056a,0x59e059e,0x59e059e,0x5d205d2,0x59e059e,0x5d205d2,
0x4320432,0x4660432,0x4320432,0x4660466,0x4660466,0x49a049a,0x4660466,0x49a049a,0x49a049a,0x4ce049a,0x49a049a,0x4ce04ce,0x4ce04ce,0x5020502,0x4ce04ce,0x5020502,
0x3620362,0x3960362,0x3620362,0x3960396,0x3960396,0x3ca03ca,0x3960396,0x3ca03ca,0x3ca03ca,0x3fe03ca,0x3ca03ca,0x3fe03fe,0x3fe03fe,0x4320432,0x3fe03fe,0x4320432,
0x2920292,0x2c60292,0x2920292,0x2c602c6,0x2c602c6,0x2fa02fa,0x2c602c6,0x2fa02fa,0x2fa02fa,0x32e02fa,0x2fa02fa,0x32e032e,0x32e032e,0x3620362,0x32e032e,0x3620362,
0x1c201c2,0x1f601c2,0x1c201c2,0x1f601f6,0x1f601f6,0x22a022a,0x1f601f6,0x22a022a,0x22a022a,0x25e022a,0x22a022a,0x25e025e,0x25e025e,0x2920292,0x25e025e,0x2920292,
0xf200f2,0x12600f2,0xf200f2,0x1260126,0x1260126,0x15a015a,0x1260126,0x15a015a,0x15a015a,0x18e015a,0x15a015a,0x18e018e,0x18e018e,0x1c201c2,0x18e018e,0x1c201c2,
0x220022,0x560022,0x220022,0x560056,0x560056,0x8a008a,0x560056,0x8a008a,0x8a008a,0xbe008a,0x8a008a,0xbe00be,0xbe00be,0xf200f2,0xbe00be,0xf200f2,
0x5d005d0,0x60405d0,0x5d005d0,0x6040604,0x6040604,0x6380638,0x6040604,0x6380638,0x6380638,0x66c0638,0x6380638,0x66c066c,0x66c066c,0x220022,0x66c066c,0x220022,
0x5000500,0x5340500,0x5000500,0x5340534,0x5340534,0x5680568,0x5340534,0x5680568,0x5680568,0x59c0568,0x5680568,0x59c059c,0x59c059c,0x5d005d0,0x59c059c,0x5d005d0,
0x4300430,0x4640430,0x4300430,0x4640464,0x4640464,0x4980498,0x4640464,0x4980498,0x4980498,0x4cc0498,0x4980498,0x4cc04cc,0x4cc04cc,0x5000500,0x4cc04cc,0x5000500,
0x3600360,0x3940360,0x3600360,0x3940394,0x3940394,0x3c803c8,0x3940394,0x3c803c8,0x3c803c8,0x3fc03c8,0x3c803c8,0x3fc03fc,0x3fc03fc,0x4300430,0x3fc03fc,0x4300430,
0x2900290,0x2c40290,0x2900290,0x2c402c4,0x2c402c4,0x2f802f8,0x2c402c4,0x2f802f8,0x2f802f8,0x32c02f8,0x2f802f8,0x32c032c,0x32c032c,0x3600360,0x32c032c,0x3600360,
0x1c001c0,0x1f401c0,0x1c001c0,0x1f401f4,0x1f401f4,0x2280228,0x1f401f4,0x2280228,0x2280228,0x25c0228,0x2280228,0x25c025c,0x25c025c,0x2900290,0x25c025c,0x2900290,
0xf000f0,0x12400f0,0xf000f0,0x1240124,0x1240124,0x1580158,0x1240124,0x1580158,0x1580158,0x18c0158,0x1580158,0x18c018c,0x18c018c,0x1c001c0,0x18c018c,0x1c001c0,
0x200020,0x540020,0x200020,0x540054,0x540054,0x880088,0x540054,0x880088,0x880088,0xbc0088,0x880088,0xbc00bc,0xbc00bc,0xf000f0,0xbc00bc,0xf000f0,
0x30003000,0x30003000,0x30003000,0x30003000,0x30003000,0x30003000,0x30003000,0x30003000,0x0,0x0,0x0,0x0,0x0,0x0,0x0,0x0,
0x30003000,0x30003000,0x30003000,0x30003000,0x30003000,0x30003000,0x30003000,0x30003000,0x0,0x0,0x0,0x0,0x0,0x0,0x0,0x0,
0x2a1f2da8,0xaf64ada8,0xaa1fada8,0x2f642da8,0x2f643000,0xaa1f0000,0xaf64b000,0x2a1f8000,0x2f642da8,0x2a1f2da8,0xaf64ada8,0xaa1fada8,0x2a1f0000,0x2f643000,0xaa1f0000,0xaf64b000,
0x263e2c72,0xafd9aea7,0xa63eac72,0x2fd92ea7,0x2ea72fd9,0xac72a63e,0xaea7afd9,0x2c72263e,0x2fd92ea7,0x263e2c72,0xafd9aea7,0xa63eac72,0x2c72263e,0x2ea72fd9,0xac72a63e,0xaea7afd9,
0x2da80000,0xada80000,0x2da88000,0xada80000,0x2da83000,0xada8b000,0x2da83000,0xada8b000,0x2da83000,0xada8b000,0x2da83000,0xada8b000,0xada80000,0x2da88000,0xada80000,0x2da88000,
0x2f642a1f,0xaf64aa1f,0x2f642a1f,0xaf64aa1f,0x2a1f2f64,0xaa1faf64,0x2a1f2f64,0xaa1faf64,0x2a1f2f64,0xaa1faf64,0x2a1f2f64,0xaa1faf64,0xaf64aa1f,0x2f642a1f,0xaf64aa1f,0x2f642a1f,
0xaa1f2da8,0x2f642da8,0x2a1fada8,0xaf64ada8,0x2f640000,0xaa1fb000,0xaf640000,0x2a1f3000,0xaf64ada8,0xaa1f2da8,0x2f642da8,0x2a1fada8,0x2a1f3000,0x2f648000,0xaa1fb000,0xaf640000,
0xaea7263e,0x2c722fd9,0x2ea7a63e,0xac72afd9,0x2fd92c72,0x263eaea7,0xafd9ac72,0xa63e2ea7,0xac72afd9,0xaea7263e,0x2c722fd9,0x2ea7a63e,0xa63e2ea7,0x2fd92c72,0x263eaea7,0xafd9ac72,
0xada82da8,0xada82da8,0xada82da8,0xada82da8,0x2da8ada8,0x2da8ada8,0x2da8ada8,0x2da8ada8,0x2da82da8,0x2da82da8,0x2da82da8,0x2da82da8,0xada8ada8,0xada8ada8,0xada8ada8,0xada8ada8,
0x3000,0x3000,0x3000,0x80003000,0x8000b000,0x8000b000,0x8000b000,0x8000b000,0x30000000,0x30008000,0x30008000,0x30008000,0xb0000000,0xb0000000,0xb0000000,0xb0000000,
0x2ea7263e,0xac722fd9,0xaea7a63e,0x2c72afd9,0xafd92c72,0xa63eaea7,0x2fd9ac72,0x263e2ea7,0x2c72afd9,0x2ea7263e,0xac722fd9,0xaea7a63e,0x263e2ea7,0xafd92c72,0xa63eaea7,0x2fd9ac72,
0x2f64ada8,0x2a1f2da8,0xaf642da8,0xaa1fada8,0xaa1f3000,0xaf640000,0x2a1fb000,0x2f648000,0xaa1fada8,0x2f64ada8,0x2a1f2da8,0xaf642da8,0x2f640000,0xaa1f3000,0xaf640000,0x2a1fb000,
0xaa1f2f64,0x2a1faf64,0xaa1f2f64,0x2a1faf64,0x2f64aa1f,0xaf642a1f,0x2f64aa1f,0xaf642a1f,0xaf642a1f,0x2f64aa1f,0xaf642a1f,0x2f64aa1f,0xaa1f2f64,0x2a1faf64,0xaa1f2f64,0x2a1faf64,
0x2da80000,0xada80000,0x2da88000,0xada80000,0x2da8b000,0xada83000,0x2da8b000,0xada83000,0xada83000,0x2da8b000,0xada83000,0x2da8b000,0x2da88000,0xada80000,0x2da88000,0xada88000,
0xa63e2c72,0x2fd9aea7,0x263eac72,0xafd92ea7,0xaea72fd9,0x2c72a63e,0x2ea7afd9,0xac72263e,0xafd92ea7,0xa63e2c72,0x2fd9aea7,0x263eac72,0xac72263e,0xaea72fd9,0x2c72a63e,0x2ea7afd9,
0x2f64ada8,0x2a1fada8,0xaf642da8,0xaa1f2da8,0x2a1f0000,0x2f64b000,0xaa1f0000,0xaf643000,0xaa1f2da8,0x2f64ada8,0x2a1fada8,0xaf642da8,0xaf643000,0x2a1f8000,0x2f64b000,0xaa1f8000,
0xb0003000,0xb0003000,0xb0003000,0xb0003000,0xb0003000,0xb0003000,0xb0003000,0xb0003000,0x0,0x8000,0x8000,0x80008000,0x8000,0x8000,0x8000,0x8000,
0x80000000,0x80000000,0x80008000,0x80008000,0x80000000,0x80008000,0x80008000,0x80008000,0xb0003000,0xb0003000,0xb0003000,0xb0003000,0xb0003000,0xb0003000,0xb0003000,0xb0003000,
0xaa1f2da8,0x2f64ada8,0x2a1fada8,0xaf642da8,0xaf643000,0x2a1f0000,0x2f64b000,0xaa1f8000,0xaf642da8,0xaa1f2da8,0x2f64ada8,0x2a1fada8,0xaa1f0000,0xaf643000,0x2a1f0000,0x2f64b000,
0x2fd9aea7,0x263eac72,0xafd92ea7,0xa63e2c72,0x2c72a63e,0x2ea7afd9,0xac72263e,0xaea72fd9,0xa63e2c72,0x2fd9aea7,0x263eac72,0xafd92ea7,0xaea72fd9,0x2c72a63e,0x2ea7afd9,0xac72263e,
0xada80000,0x2da80000,0xada88000,0x2da80000,0xada83000,0x2da8b000,0xada83000,0x2da8b000,0xada83000,0x2da8b000,0xada83000,0x2da8b000,0x2da80000,0xada88000,0x2da88000,0xada88000,
0xaa1f2f64,0x2a1faf64,0xaa1f2f64,0x2a1faf64,0x2f64aa1f,0xaf642a1f,0x2f64aa1f,0xaf642a1f,0x2f64aa1f,0xaf642a1f,0x2f64aa1f,0xaf642a1f,0x2a1faf64,0xaa1f2f64,0x2a1faf64,0xaa1f2f64,
0x2a1f2da8,0xaf642da8,0xaa1fada8,0x2f64ada8,0xaf640000,0x2a1fb000,0x2f640000,0xaa1f3000,0x2f64ada8,0x2a1f2da8,0xaf642da8,0xaa1fada8,0xaa1f3000,0xaf648000,0x2a1fb000,0x2f640000,
0x2c72afd9,0x2ea7263e,0xac722fd9,0xaea7a63e,0x263e2ea7,0xafd92c72,0xa63eaea7,0x2fd9ac72,0xaea7a63e,0x2c72afd9,0x2ea7263e,0xac722fd9,0x2fd9ac72,0x263e2ea7,0xafd92c72,0xa63eaea7,
0x2da8ada8,0x2da8ada8,0x2da8ada8,0x2da8ada8,0xada82da8,0xada82da8,0xada82da8,0xada82da8,0x2da82da8,0x2da82da8,0x2da82da8,0x2da82da8,0xada8ada8,0xada8ada8,0xada8ada8,0xada8ada8,
0x80003000,0x80003000,0x80003000,0x3000,0xb000,0x8000b000,0xb000,0xb000,0xb0000000,0xb0008000,0xb0008000,0xb0008000,0x30000000,0x30000000,0x30000000,0x30008000,
0x2c722fd9,0x2ea7a63e,0xac72afd9,0xaea7263e,0x263eaea7,0xafd9ac72,0xa63e2ea7,0x2fd92c72,0xaea7263e,0x2c722fd9,0x2ea7a63e,0xac72afd9,0x2fd92c72,0x263eaea7,0xafd9ac72,0xa63e2ea7,
0xaf64ada8,0xaa1f2da8,0x2f642da8,0x2a1fada8,0x2a1f3000,0x2f648000,0xaa1fb000,0xaf648000,0x2a1fada8,0xaf64ada8,0xaa1f2da8,0x2f642da8,0xaf640000,0x2a1f3000,0x2f648000,0xaa1fb000,
0x2f642a1f,0xaf64aa1f,0x2f642a1f,0xaf64aa1f,0x2a1f2f64,0xaa1faf64,0x2a1f2f64,0xaa1faf64,0xaa1faf64,0x2a1f2f64,0xaa1faf64,0x2a1f2f64,0x2f642a1f,0xaf64aa1f,0x2f642a1f,0xaf64aa1f,
0xada80000,0x2da80000,0xada88000,0x2da88000,0xada8b000,0x2da83000,0xada8b000,0x2da83000,0x2da83000,0xada8b000,0x2da83000,0xada8b000,0xada88000,0x2da88000,0xada88000,0x2da80000,
0x2fd92ea7,0x263e2c72,0xafd9aea7,0xa63eac72,0x2c72263e,0x2ea72fd9,0xac72a63e,0xaea7afd9,0xa63eac72,0x2fd92ea7,0x263e2c72,0xafd9aea7,0xaea7afd9,0x2c72263e,0x2ea72fd9,0xac72a63e,
0xaf64ada8,0xaa1fada8,0x2f642da8,0x2a1f2da8,0xaa1f0000,0xaf64b000,0x2a1f0000,0x2f643000,0x2a1f2da8,0xaf64ada8,0xaa1fada8,0x2f642da8,0x2f643000,0xaa1f8000,0xaf64b000,0x2a1f0000,
0x80008000,0x80008000,0x80008000,0x80008000,0x80008000,0x80008000,0x80008000,0x80008000,0x30003000,0x30003000,0x30003000,0x30003000,0x30003000,0x30003000,0x30003000,0x30003000,
0x80008000,0x80008000,0x80008000,0x80008000,0x80008000,0x80008000,0x80008000,0x80008000,0x30003000,0x30003000,0x30003000,0x30003000,0x30003000,0x30003000,0x30003000,0x30003000,
0xaf64ada8,0xaa1fada8,0x2f642da8,0x2a1f2da8,0xaa1f8000,0xaf64b000,0x2a1f8000,0x2f643000,0x2a1f2da8,0xaf64ada8,0xaa1fada8,0x2f642da8,0x2f643000,0xaa1f0000,0xaf64b000,0x2a1f8000,
0xafd9aea7,0xa63eac72,0x2fd92ea7,0x263e2c72,0xac72a63e,0xaea7afd9,0x2c72263e,0x2ea72fd9,0x263e2c72,0xafd9aea7,0xa63eac72,0x2fd92ea7,0x2ea72fd9,0xac72a63e,0xaea7afd9,0x2c72263e,
0x2da83000,0xada8b000,0x2da83000,0xada8b000,0xada80000,0x2da88000,0xada80000,0x2da88000,0xada88000,0x2da88000,0xada80000,0x2da88000,0xada8b000,0x2da83000,0xada8b000,0x2da83000,
0x2a1f2f64,0xaa1faf64,0x2a1f2f64,0xaa1faf64,0xaf64aa1f,0x2f642a1f,0xaf64aa1f,0x2f642a1f,0xaf64aa1f,0x2f642a1f,0xaf64aa1f,0x2f642a1f,0xaa1faf64,0x2a1f2f64,0xaa1faf64,0x2a1f2f64,
0xaf64ada8,0xaa1f2da8,0x2f642da8,0x2a1fada8,0x2a1f3000,0x2f648000,0xaa1fb000,0xaf640000,0x2a1fada8,0xaf64ada8,0xaa1f2da8,0x2f642da8,0xaf648000,0x2a1f3000,0x2f648000,0xaa1fb000,
0xac72afd9,0xaea7263e,0x2c722fd9,0x2ea7a63e,0xa63e2ea7,0x2fd92c72,0x263eaea7,0xafd9ac72,0x2ea7a63e,0xac72afd9,0xaea7263e,0x2c722fd9,0xafd9ac72,0xa63e2ea7,0x2fd92c72,0x263eaea7,
0xada8ada8,0xada8ada8,0xada8ada8,0xada8ada8,0x2da82da8,0x2da82da8,0x2da82da8,0x2da82da8,0xada82da8,0xada82da8,0xada82da8,0xada82da8,0x2da8ada8,0x2da8ada8,0x2da8ada8,0x2da8ada8,
0xb0008000,0xb0000000,0xb0000000,0xb0000000,0x30008000,0x30008000,0x30008000,0x30008000,0x3000,0x3000,0x3000,0x80003000,0x8000b000,0x8000b000,0x8000b000,0x8000b000,
0xac722fd9,0xaea7a63e,0x2c72afd9,0x2ea7263e,0xa63eaea7,0x2fd9ac72,0x263e2ea7,0xafd92c72,0x2ea7263e,0xac722fd9,0xaea7a63e,0x2c72afd9,0xafd92c72,0xa63eaea7,0x2fd9ac72,0x263e2ea7,
0x2a1f2da8,0xaf642da8,0xaa1fada8,0x2f64ada8,0xaf648000,0x2a1fb000,0x2f648000,0xaa1f3000,0x2f64ada8,0x2a1f2da8,0xaf642da8,0xaa1fada8,0xaa1f3000,0xaf640000,0x2a1fb000,0x2f648000,
0xaf642a1f,0x2f64aa1f,0xaf642a1f,0x2f64aa1f,0xaa1f2f64,0x2a1faf64,0xaa1f2f64,0x2a1faf64,0x2a1faf64,0xaa1f2f64,0x2a1faf64,0xaa1f2f64,0xaf642a1f,0x2f64aa1f,0xaf642a1f,0x2f64aa1f,
0xada83000,0x2da8b000,0xada83000,0x2da8b000,0x2da88000,0xada80000,0x2da88000,0xada88000,0xada88000,0x2da88000,0xada80000,0x2da88000,0xada83000,0x2da8b000,0xada83000,0x2da8b000,
0xafd92ea7,0xa63e2c72,0x2fd9aea7,0x263eac72,0xac72263e,0xaea72fd9,0x2c72a63e,0x2ea7afd9,0x263eac72,0xafd92ea7,0xa63e2c72,0x2fd9aea7,0x2ea7afd9,0xac72263e,0xaea72fd9,0x2c72a63e,
0xaa1f2da8,0x2f64ada8,0x2a1fada8,0xaf642da8,0xaf643000,0x2a1f8000,0x2f64b000,0xaa1f8000,0xaf642da8,0xaa1f2da8,0x2f64ada8,0x2a1fada8,0xaa1f8000,0xaf643000,0x2a1f8000,0x2f64b000,
0x80008000,0x80000000,0x80000000,0x0,0x80000000,0x80000000,0x80000000,0x80000000,0xb0003000,0xb0003000,0xb0003000,0xb0003000,0xb0003000,0xb0003000,0xb0003000,0xb0003000,
0x3000b000,0x3000b000,0x3000b000,0x3000b000,0x3000b000,0x3000b000,0x3000b000,0x3000b000,0x80000000,0x80000000,0x80008000,0x80008000,0x80000000,0x80008000,0x80008000,0x80008000,
0x2f64ada8,0x2a1fada8,0xaf642da8,0xaa1f2da8,0x2a1f8000,0x2f64b000,0xaa1f8000,0xaf643000,0xaa1f2da8,0x2f64ada8,0x2a1fada8,0xaf642da8,0xaf643000,0x2a1f0000,0x2f64b000,0xaa1f8000,
0x263eac72,0xafd92ea7,0xa63e2c72,0x2fd9aea7,0x2ea7afd9,0xac72263e,0xaea72fd9,0x2c72a63e,0x2fd9aea7,0x263eac72,0xafd92ea7,0xa63e2c72,0x2c72a63e,0x2ea7afd9,0xac72263e,0xaea72fd9,
0xada83000,0x2da8b000,0xada83000,0x2da8b000,0x2da80000,0xada88000,0x2da88000,0xada88000,0x2da88000,0xada88000,0x2da80000,0xada88000,0x2da8b000,0xada83000,0x2da8b000,0xada83000,
0x2f64aa1f,0xaf642a1f,0x2f64aa1f,0xaf642a1f,0x2a1faf64,0xaa1f2f64,0x2a1faf64,0xaa1f2f64,0x2a1faf64,0xaa1f2f64,0x2a1faf64,0xaa1f2f64,0xaf642a1f,0x2f64aa1f,0xaf642a1f,0x2f64aa1f,
0x2f64ada8,0x2a1f2da8,0xaf642da8,0xaa1fada8,0xaa1f3000,0xaf648000,0x2a1fb000,0x2f640000,0xaa1fada8,0x2f64ada8,0x2a1f2da8,0xaf642da8,0x2f648000,0xaa1f3000,0xaf648000,0x2a1fb000,
0xaea7a63e,0x2c72afd9,0x2ea7263e,0xac722fd9,0x2fd9ac72,0x263e2ea7,0xafd92c72,0xa63eaea7,0xac722fd9,0xaea7a63e,0x2c72afd9,0x2ea7263e,0xa63eaea7,0x2fd9ac72,0x263e2ea7,0xafd92c72,
0xada8ada8,0xada8ada8,0xada8ada8,0xada8ada8,0x2da82da8,0x2da82da8,0x2da82da8,0x2da82da8,0x2da8ada8,0x2da8ada8,0x2da8ada8,0x2da8ada8,0xada82da8,0xada82da8,0xada82da8,0xada82da8,
0x30008000,0x30000000,0x30000000,0x30000000,0xb0008000,0xb0008000,0xb0008000,0xb0000000,0x80003000,0x80003000,0x80003000,0x3000,0xb000,0x8000b000,0xb000,0xb000,
0x2ea7a63e,0xac72afd9,0xaea7263e,0x2c722fd9,0xafd9ac72,0xa63e2ea7,0x2fd92c72,0x263eaea7,0x2c722fd9,0x2ea7a63e,0xac72afd9,0xaea7263e,0x263eaea7,0xafd9ac72,0xa63e2ea7,0x2fd92c72,
0xaa1f2da8,0x2f642da8,0x2a1fada8,0xaf64ada8,0x2f648000,0xaa1fb000,0xaf640000,0x2a1f3000,0xaf64ada8,0xaa1f2da8,0x2f642da8,0x2a1fada8,0x2a1f3000,0x2f648000,0xaa1fb000,0xaf648000,
0xaa1faf64,0x2a1f2f64,0xaa1faf64,0x2a1f2f64,0x2f642a1f,0xaf64aa1f,0x2f642a1f,0xaf64aa1f,0xaf64aa1f,0x2f642a1f,0xaf64aa1f,0x2f642a1f,0xaa1faf64,0x2a1f2f64,0xaa1faf64,0x2a1f2f64,
0x2da83000,0xada8b000,0x2da83000,0xada8b000,0xada88000,0x2da88000,0xada88000,0x2da80000,0x2da88000,0xada88000,0x2da80000,0xada80000,0x2da83000,0xada8b000,0x2da83000,0xada8b000,
0xa63eac72,0x2fd92ea7,0x263e2c72,0xafd9aea7,0xaea7afd9,0x2c72263e,0x2ea72fd9,0xac72a63e,0xafd9aea7,0xa63eac72,0x2fd92ea7,0x263e2c72,0xac72a63e,0xaea7afd9,0x2c72263e,0x2ea72fd9,
0x2a1f2da8,0xaf64ada8,0xaa1fada8,0x2f642da8,0x2f643000,0xaa1f8000,0xaf64b000,0x2a1f0000,0x2f642da8,0x2a1f2da8,0xaf64ada8,0xaa1fada8,0x2a1f8000,0x2f643000,0xaa1f8000,0xaf64b000,
0x3c003c00,0x3c003c00,0x3c003c00,0x3c003c00,0x3c003c00,0x3c003c00,0x3c003c00,0x3c003c00,0x80008000,0x80008000,0x80008000,0x80008000,0x80008000,0x80008000,0x80008000,0x80008000,
0x3bd93c00,0x3aa73b64,0x387239a8,0x323e361f,0xb23e0000,0xb872b61f,0xbaa7b9a8,0xbbd9bb64,0xb23e8000,0xb872b61f,0xbaa7b9a8,0xbbd9bb64,0xbbd9bc00,0xbaa7bb64,0xb872b9a8,0xb23eb61f,
0xbb64bc00,0xb61fb9a8,0x361f8000,0x3b6439a8,0x3b643c00,0x361f39a8,0xb61f0000,0xbb64b9a8,0x361f8000,0x3b6439a8,0x3b643c00,0x361f39a8,0xb61f8000,0xbb64b9a8,0xbb64bc00,0xb61fb9a8,
0x38728000,0x3bd93b64,0x323e39a8,0xbaa7b61f,0x3aa73c00,0xb23e361f,0xbbd9b9a8,0xb872bb64,0x3aa73c00,0xb23e361f,0xbbd9b9a8,0xb872bb64,0xb8728000,0xbbd9bb64,0xb23eb9a8,0x3aa7361f,
0xbc008000,0x3c008000,0xbc000000,0x3c008000,0xbc000000,0x3c008000,0xbc000000,0x3c008000,0x3c00,0x8000bc00,0x3c00,0x8000bc00,0x3c00,0x8000bc00,0x80003c00,0x8000bc00,
0xbbd98000,0x3aa7361f,0xb872b9a8,0x323e3b64,0x323ebc00,0xb8723b64,0x3aa7b9a8,0xbbd9361f,0xb23e3c00,0x3872bb64,0xbaa739a8,0x3bd9b61f,0xbbd90000,0x3aa7361f,0xb872b9a8,0x323e3b64,
0x3b648000,0xb61fb9a8,0xb61f3c00,0x3b64b9a8,0xbb648000,0x361f39a8,0x361fbc00,0xbb6439a8,0x361fbc00,0xbb6439a8,0x3b648000,0xb61fb9a8,0xb61f3c00,0x3b64b9a8,0xbb640000,0x361f39a8,
0xb8723c00,0x3bd9b61f,0xb23eb9a8,0xbaa73b64,0xbaa78000,0xb23e3b64,0x3bd9b9a8,0xb872b61f,0x3aa78000,0x323ebb64,0xbbd939a8,0x3872361f,0xb8723c00,0x3bd9b61f,0xb23eb9a8,0xbaa73b64,
0xbbd93c00,0xbaa73b64,0xb87239a8,0xb23e361f,0x323e8000,0x3872b61f,0x3aa7b9a8,0x3bd9bb64,0x323e8000,0x3872b61f,0x3aa7b9a8,0x3bd9bb64,0x3bd9bc00,0x3aa7bb64,0x3872b9a8,0x323eb61f,
0xbc003c00,0xbc003c00,0xbc003c00,0xbc003c00,0xbc003c00,0xbc003c00,0xbc003c00,0xbc003c00,0x80008000,0x80000000,0x80000000,0x80000000,0x80000000,0x80000000,0x0,0x80000000,
0xb8728000,0xbbd93b64,0xb23e39a8,0x3aa7b61f,0xbaa73c00,0x323e361f,0x3bd9b9a8,0x3872bb64,0xbaa73c00,0x323e361f,0x3bd9b9a8,0x3872bb64,0x38728000,0x3bd9bb64,0x323eb9a8,0xbaa7361f,
0x3b64bc00,0x361fb9a8,0xb61f8000,0xbb6439a8,0xbb643c00,0xb61f39a8,0x361f0000,0x3b64b9a8,0xb61f8000,0xbb6439a8,0xbb643c00,0xb61f39a8,0x361f8000,0x3b64b9a8,0x3b64bc00,0x361fb9a8,
0x3bd98000,0xbaa7361f,0x3872b9a8,0xb23e3b64,0xb23ebc00,0x38723b64,0xbaa7b9a8,0x3bd9361f,0x323e3c00,0xb872bb64,0x3aa739a8,0xbbd9b61f,0x3bd98000,0xbaa7361f,0x3872b9a8,0xb23e3b64,
0x3c008000,0xbc008000,0x3c000000,0xbc008000,0x3c000000,0xbc008000,0x3c000000,0xbc000000,0x80003c00,0xbc00,0x80003c00,0x8000bc00,0x80003c00,0xbc00,0x80003c00,0xbc00,
0x38723c00,0xbbd9b61f,0x323eb9a8,0x3aa73b64,0x3aa78000,0x323e3b64,0xbbd9b9a8,0x3872b61f,0xbaa78000,0xb23ebb64,0x3bd939a8,0xb872361f,0x38723c00,0xbbd9b61f,0x323eb9a8,0x3aa73b64,
0xbb640000,0x361fb9a8,0x361f3c00,0xbb64b9a8,0x3b648000,0xb61f39a8,0xb61fbc00,0x3b6439a8,0xb61fbc00,0x3b6439a8,0xbb640000,0x361fb9a8,0x361f3c00,0xbb64b9a8,0x3b648000,0xb61f39a8,
0x39a83c00,0xb9a80000,0xb9a8bc00,0x39a88000,0x39a83c00,0xb9a80000,0xb9a8bc00,0x39a88000,0xb9a88000,0xb9a8bc00,0x39a88000,0x39a83c00,0xb9a80000,0xb9a8bc00,0x39a88000,0x39a83c00,
0x38723c00,0xbbd9b61f,0x323eb9a8,0x3aa73b64,0xbaa70000,0xb23ebb64,0x3bd939a8,0xb872361f,0xbaa78000,0xb23ebb64,0x3bd939a8,0xb872361f,0xb872bc00,0x3bd9361f,0xb23e39a8,0xbaa7bb64,
0xb61fbc00,0x3b6439a8,0xbb640000,0x361fb9a8,0x361f3c00,0xbb64b9a8,0x3b648000,0xb61f39a8,0x3b648000,0xb61f39a8,0xb61fbc00,0x3b6439a8,0xbb648000,0x361fb9a8,0x361f3c00,0xbb64b9a8,
0x3bd98000,0xbaa7361f,0x3872b9a8,0xb23e3b64,0x323e3c00,0xb872bb64,0x3aa739a8,0xbbd9b61f,0x323e3c00,0xb872bb64,0x3aa739a8,0xbbd9b61f,0xbbd98000,0x3aa7b61f,0xb87239a8,0x323ebb64,
0xb9a88000,0xb9a83c00,0x39a88000,0x39a8bc00,0xb9a80000,0xb9a83c00,0x39a88000,0x39a8bc00,0xb9a83c00,0x39a88000,0x39a8bc00,0xb9a80000,0xb9a83c00,0x39a88000,0x39a8bc00,0xb9a88000,
0xb8728000,0xbbd93b64,0xb23e39a8,0x3aa7b61f,0x3aa7bc00,0xb23eb61f,0xbbd939a8,0xb8723b64,0xbaa73c00,0x323e361f,0x3bd9b9a8,0x3872bb64,0xb8728000,0xbbd93b64,0xb23e39a8,0x3aa7b61f,
0x361f8000,0x3b64b9a8,0x3b64bc00,0x361fb9a8,0xb61f8000,0xbb6439a8,0xbb643c00,0xb61f39a8,0x3b64bc00,0x361fb9a8,0xb61f8000,0xbb6439a8,0xbb643c00,0xb61f39a8,0x361f8000,0x3b64b9a8,
0xbbd93c00,0xbaa73b64,0xb87239a8,0xb23e361f,0xb23e8000,0xb872361f,0xbaa739a8,0xbbd93b64,0x323e8000,0x3872b61f,0x3aa7b9a8,0x3bd9bb64,0xbbd93c00,0xbaa73b64,0xb87239a8,0xb23e361f,
0xb8723c00,0x3bd9b61f,0xb23eb9a8,0xbaa73b64,0x3aa78000,0x323ebb64,0xbbd939a8,0x3872361f,0x3aa78000,0x323ebb64,0xbbd939a8,0x3872361f,0x3872bc00,0xbbd9361f,0x323e39a8,0x3aa7bb64,
0xb9a83c00,0x39a80000,0x39a8bc00,0xb9a88000,0xb9a83c00,0x39a88000,0x39a8bc00,0xb9a88000,0x39a88000,0x39a8bc00,0xb9a88000,0xb9a83c00,0x39a80000,0x39a8bc00,0xb9a88000,0xb9a83c00,
0xbbd98000,0x3aa7361f,0xb872b9a8,0x323e3b64,0xb23e3c00,0x3872bb64,0xbaa739a8,0x3bd9b61f,0xb23e3c00,0x3872bb64,0xbaa739a8,0x3bd9b61f,0x3bd98000,0xbaa7b61f,0x387239a8,0xb23ebb64,
0x361fbc00,0xbb6439a8,0x3b640000,0xb61fb9a8,0xb61f3c00,0x3b64b9a8,0xbb648000,0x361f39a8,0xbb648000,0x361f39a8,0x361fbc00,0xbb6439a8,0x3b648000,0xb61fb9a8,0xb61f3c00,0x3b64b9a8,
0x38728000,0x3bd93b64,0x323e39a8,0xbaa7b61f,0xbaa7bc00,0x323eb61f,0x3bd939a8,0x38723b64,0x3aa73c00,0xb23e361f,0xbbd9b9a8,0xb872bb64,0x38728000,0x3bd93b64,0x323e39a8,0xbaa7b61f,
0x39a88000,0x39a83c00,0xb9a88000,0xb9a8bc00,0x39a80000,0x39a83c00,0xb9a80000,0xb9a8bc00,0x39a83c00,0xb9a88000,0xb9a8bc00,0x39a88000,0x39a83c00,0xb9a88000,0xb9a8bc00,0x39a80000,
0x3bd93c00,0x3aa73b64,0x387239a8,0x323e361f,0x323e8000,0x3872361f,0x3aa739a8,0x3bd93b64,0xb23e8000,0xb872b61f,0xbaa7b9a8,0xbbd9bb64,0x3bd93c00,0x3aa73b64,0x387239a8,0x323e361f,
0xb61f8000,0xbb64b9a8,0xbb64bc00,0xb61fb9a8,0x361f8000,0x3b6439a8,0x3b643c00,0x361f39a8,0xbb64bc00,0xb61fb9a8,0x361f0000,0x3b6439a8,0x3b643c00,0x361f39a8,0xb61f8000,0xbb64b9a8,
0x0,0x0,0x0,0x0,0x0,0x0,0x0,0x0,0x3c003c00,0x3c003c00,0x3c003c00,0x3c003c00,0x3c003c00,0x3c003c00,0x3c003c00,0x3c003c00,
0x323e0000,0x3872361f,0x3aa739a8,0x3bd93b64,0x3bd93c00,0x3aa73b64,0x387239a8,0x323e361f,0x3bd93c00,0x3aa73b64,0x387239a8,0x323e361f,0xb23e0000,0xb872b61f,0xbaa7b9a8,0xbbd9bb64,
0xb61f0000,0xbb64b9a8,0xbb64bc00,0xb61fb9a8,0x361f0000,0x3b6439a8,0x3b643c00,0x361f39a8,0xbb64bc00,0xb61fb9a8,0x361f8000,0x3b6439a8,0x3b643c00,0x361f39a8,0xb61f0000,0xbb64b9a8,
0xbaa7bc00,0x323eb61f,0x3bd939a8,0x38723b64,0x38720000,0x3bd93b64,0x323e39a8,0xbaa7b61f,0x38728000,0x3bd93b64,0x323e39a8,0xbaa7b61f,0x3aa73c00,0xb23e361f,0xbbd9b9a8,0xb872bb64,
0x3c00,0x8000bc00,0x3c00,0x8000bc00,0x3c00,0x8000bc00,0x80003c00,0x8000bc00,0x3c000000,0xbc000000,0x3c008000,0xbc000000,0x3c008000,0xbc000000,0x3c008000,0xbc000000,
0xb23e3c00,0x3872bb64,0xbaa739a8,0x3bd9b61f,0xbbd90000,0x3aa7361f,0xb872b9a8,0x323e3b64,0x3bd90000,0xbaa7b61f,0x387239a8,0xb23ebb64,0xb23e3c00,0x3872bb64,0xbaa739a8,0x3bd9b61f,
0x361fbc00,0xbb6439a8,0x3b648000,0xb61fb9a8,0xb61f3c00,0x3b64b9a8,0xbb640000,0x361f39a8,0xbb640000,0x361f39a8,0x361fbc00,0xbb6439a8,0x3b640000,0xb61fb9a8,0xb61f3c00,0x3b64b9a8,
0x3aa78000,0x323ebb64,0xbbd939a8,0x3872361f,0xb8723c00,0x3bd9b61f,0xb23eb9a8,0xbaa73b64,0x3872bc00,0xbbd9361f,0x323e39a8,0x3aa7bb64,0x3aa70000,0x323ebb64,0xbbd939a8,0x3872361f,
0xb23e0000,0xb872361f,0xbaa739a8,0xbbd93b64,0xbbd93c00,0xbaa73b64,0xb87239a8,0xb23e361f,0xbbd93c00,0xbaa73b64,0xb87239a8,0xb23e361f,0x323e8000,0x3872b61f,0x3aa7b9a8,0x3bd9bb64,
0x0,0x8000,0x8000,0x8000,0x8000,0x8000,0x80008000,0x8000,0xbc003c00,0xbc003c00,0xbc003c00,0xbc003c00,0xbc003c00,0xbc003c00,0xbc003c00,0xbc003c00,
0x3aa7bc00,0xb23eb61f,0xbbd939a8,0xb8723b64,0xb8720000,0xbbd93b64,0xb23e39a8,0x3aa7b61f,0xb8728000,0xbbd93b64,0xb23e39a8,0x3aa7b61f,0xbaa73c00,0x323e361f,0x3bd9b9a8,0x3872bb64,
0x361f0000,0x3b64b9a8,0x3b64bc00,0x361fb9a8,0xb61f0000,0xbb6439a8,0xbb643c00,0xb61f39a8,0x3b64bc00,0x361fb9a8,0xb61f8000,0xbb6439a8,0xbb643c00,0xb61f39a8,0x361f0000,0x3b64b9a8,
0x323e3c00,0xb872bb64,0x3aa739a8,0xbbd9b61f,0x3bd98000,0xbaa7361f,0x3872b9a8,0xb23e3b64,0xbbd90000,0x3aa7b61f,0xb87239a8,0x323ebb64,0x323e3c00,0xb872bb64,0x3aa739a8,0xbbd9b61f,
0x80003c00,0xbc00,0x80003c00,0x8000bc00,0x80003c00,0xbc00,0x80003c00,0xbc00,0xbc000000,0x3c000000,0xbc008000,0x3c000000,0xbc008000,0x3c000000,0xbc008000,0x3c008000,
0xbaa78000,0xb23ebb64,0x3bd939a8,0xb872361f,0x38723c00,0xbbd9b61f,0x323eb9a8,0x3aa73b64,0xb872bc00,0x3bd9361f,0xb23e39a8,0xbaa7bb64,0xbaa70000,0xb23ebb64,0x3bd939a8,0xb872361f,
0xb61fbc00,0x3b6439a8,0xbb640000,0x361fb9a8,0x361f3c00,0xbb64b9a8,0x3b648000,0xb61f39a8,0x3b648000,0xb61f39a8,0xb61fbc00,0x3b6439a8,0xbb640000,0x361fb9a8,0x361f3c00,0xbb64b9a8,
0x39a80000,0x39a83c00,0xb9a80000,0xb9a8bc00,0x39a88000,0x39a83c00,0xb9a80000,0xb9a8bc00,0x39a83c00,0xb9a80000,0xb9a8bc00,0x39a88000,0x39a83c00,0xb9a80000,0xb9a8bc00,0x39a88000,
0x3aa70000,0x323e3b64,0xbbd9b9a8,0x3872b61f,0x38723c00,0xbbd9b61f,0x323eb9a8,0x3aa73b64,0x38723c00,0xbbd9b61f,0x323eb9a8,0x3aa73b64,0xbaa70000,0xb23ebb64,0x3bd939a8,0xb872361f,
0xbb640000,0x361fb9a8,0x361f3c00,0xbb64b9a8,0x3b640000,0xb61f39a8,0xb61fbc00,0x3b6439a8,0xb61fbc00,0x3b6439a8,0xbb640000,0x361fb9a8,0x361f3c00,0xbb64b9a8,0x3b648000,0xb61f39a8,
0xb23ebc00,0x38723b64,0xbaa7b9a8,0x3bd9361f,0x3bd90000,0xbaa7361f,0x3872b9a8,0xb23e3b64,0x3bd98000,0xbaa7361f,0x3872b9a8,0xb23e3b64,0x323e3c00,0xb872bb64,0x3aa739a8,0xbbd9b61f,
0xb9a83c00,0x39a88000,0x39a8bc00,0xb9a80000,0xb9a83c00,0x39a88000,0x39a8bc00,0xb9a88000,0x39a80000,0x39a8bc00,0xb9a80000,0xb9a83c00,0x39a88000,0x39a8bc00,0xb9a80000,0xb9a83c00,
0xbaa73c00,0x323e361f,0x3bd9b9a8,0x3872bb64,0xb8728000,0xbbd93b64,0xb23e39a8,0x3aa7b61f,0x38720000,0x3bd9bb64,0x323eb9a8,0xbaa7361f,0xbaa73c00,0x323e361f,0x3bd9b9a8,0x3872bb64,
0x3b64bc00,0x361fb9a8,0xb61f8000,0xbb6439a8,0xbb643c00,0xb61f39a8,0x361f8000,0x3b64b9a8,0xb61f0000,0xbb6439a8,0xbb643c00,0xb61f39a8,0x361f0000,0x3b64b9a8,0x3b64bc00,0x361fb9a8,
0x323e8000,0x3872b61f,0x3aa7b9a8,0x3bd9bb64,0xbbd93c00,0xbaa73b64,0xb87239a8,0xb23e361f,0x3bd9bc00,0x3aa7bb64,0x3872b9a8,0x323eb61f,0x323e0000,0x3872b61f,0x3aa7b9a8,0x3bd9bb64,
0xbaa70000,0xb23e3b64,0x3bd9b9a8,0xb872b61f,0xb8723c00,0x3bd9b61f,0xb23eb9a8,0xbaa73b64,0xb8723c00,0x3bd9b61f,0xb23eb9a8,0xbaa73b64,0x3aa78000,0x323ebb64,0xbbd939a8,0x3872361f,
0xb9a80000,0xb9a83c00,0x39a80000,0x39a8bc00,0xb9a88000,0xb9a83c00,0x39a80000,0x39a8bc00,0xb9a83c00,0x39a80000,0x39a8bc00,0xb9a88000,0xb9a83c00,0x39a88000,0x39a8bc00,0xb9a88000,
0x323ebc00,0xb8723b64,0x3aa7b9a8,0xbbd9361f,0xbbd90000,0x3aa7361f,0xb872b9a8,0x323e3b64,0xbbd98000,0x3aa7361f,0xb872b9a8,0x323e3b64,0xb23e3c00,0x3872bb64,0xbaa739a8,0x3bd9b61f,
0x3b640000,0xb61fb9a8,0xb61f3c00,0x3b64b9a8,0xbb640000,0x361f39a8,0x361fbc00,0xbb6439a8,0x361fbc00,0xbb6439a8,0x3b640000,0xb61fb9a8,0xb61f3c00,0x3b64b9a8,0xbb648000,0x361f39a8,
0x3aa73c00,0xb23e361f,0xbbd9b9a8,0xb872bb64,0x38728000,0x3bd93b64,0x323e39a8,0xbaa7b61f,0xb8720000,0xbbd9bb64,0xb23eb9a8,0x3aa7361f,0x3aa73c00,0xb23e361f,0xbbd9b9a8,0xb872bb64,
0x39a83c00,0xb9a88000,0xb9a8bc00,0x39a88000,0x39a83c00,0xb9a88000,0xb9a8bc00,0x39a80000,0xb9a80000,0xb9a8bc00,0x39a80000,0x39a83c00,0xb9a88000,0xb9a8bc00,0x39a88000,0x39a83c00,
0xb23e8000,0xb872b61f,0xbaa7b9a8,0xbbd9bb64,0x3bd93c00,0x3aa73b64,0x387239a8,0x323e361f,0xbbd9bc00,0xbaa7bb64,0xb872b9a8,0xb23eb61f,0xb23e0000,0xb872b61f,0xbaa7b9a8,0xbbd9bb64,
0xbb64bc00,0xb61fb9a8,0x361f0000,0x3b6439a8,0x3b643c00,0x361f39a8,0xb61f8000,0xbb64b9a8,0x361f0000,0x3b6439a8,0x3b643c00,0x361f39a8,0xb61f0000,0xbb64b9a8,0xbb64bc00,0xb61fb9a8,
};
__device__ __align__(1024) bf16 g_x1T[DM * XP];
__device__ __align__(1024) bf16 g_x2T[DM * XP];
__device__ __align__(1024) uint4 g_of[8][16][1280];
#define S_REP 1
__device__ __align__(1024) float g_fs[S_REP][2][SEQ];

#define TS_SMEM 0
#define TS_DECL
#define TS_ARG
#define TS_PASS
#define TS_PHASE(p)
#define TS(i)
#define TSX(row, i)
#define TS_BEGIN
#define TS_END

struct cplx { float r, i; };
__device__ __forceinline__ cplx cmul(cplx a, cplx b) {
    cplx o;
    o.r = fmaf(a.r, b.r, -a.i * b.i);
    o.i = fmaf(a.r, b.i, a.i * b.r);
    return o;
}
__device__ __forceinline__ cplx csq(cplx a) {
    cplx o;
    o.r = fmaf(a.r, a.r, -a.i * a.i);
    o.i = 2.f * a.r * a.i;
    return o;
}
__device__ __forceinline__ cplx cexp_p(float arl, float ai, float p) {
    float mag = ex2(arl * p);
    float ang = ai * p;
    float n = rintf(ang * 0.15915494309189535f);
    float r = fmaf(n, -6.2831854820251465f, ang);
    r = fmaf(n, 1.7484555e-7f, r);
    cplx o;
    o.r = mag * __cosf(r);
    o.i = mag * __sinf(r);
    return o;
}

__device__ __forceinline__ uint32_t pack2h(float lo, float hi) {
    uint32_t r;
    asm("cvt.rn.f16x2.f32 %0, %1, %2;" : "=r"(r) : "f"(hi), "f"(lo));
    return r;
}
__device__ __forceinline__ uint32_t hmul(uint32_t a, uint32_t b) { uint32_t d; asm("mul.rn.f16x2 %0, %1, %2;" : "=r"(d) : "r"(a), "r"(b)); return d; }
__device__ __forceinline__ uint32_t hfma(uint32_t a, uint32_t b, uint32_t c) { uint32_t d; asm("fma.rn.f16x2 %0, %1, %2, %3;" : "=r"(d) : "r"(a), "r"(b), "r"(c)); return d; }
__device__ __forceinline__ uint32_t hfms(uint32_t a, uint32_t b, uint32_t c) {
    uint32_t d;
    asm("{\n.reg .b32 n;\nneg.f16x2 n, %1;\nfma.rn.f16x2 %0, n, %2, %3;\n}" : "=r"(d) : "r"(a), "r"(b), "r"(c));
    return d;
}
__device__ __forceinline__ uint32_t hadd(uint32_t a, uint32_t b) { uint32_t d; asm("add.rn.f16x2 %0, %1, %2;" : "=r"(d) : "r"(a), "r"(b)); return d; }
__device__ __forceinline__ uint32_t hsub(uint32_t a, uint32_t b) { uint32_t d; asm("sub.rn.f16x2 %0, %1, %2;" : "=r"(d) : "r"(a), "r"(b)); return d; }
__device__ __forceinline__ uint4 ldg_tab(int tab, int t) { return ldg128((const uint4*)c_fft + t + tab * 128); }
__device__ __forceinline__ uint32_t u4(const uint4& v, int i) { return i == 0 ? v.x : i == 1 ? v.y : i == 2 ? v.z : v.w; }
struct cpair { uint32_t r, i; };
__device__ __forceinline__ cpair pmul(cpair p, uint32_t z) {
    const __half2 zv = *reinterpret_cast<const __half2*>(&z), pr = *reinterpret_cast<const __half2*>(&p.r), pi = *reinterpret_cast<const __half2*>(&p.i);
    const __half2 zr = __low2half2(zv), zi = __high2half2(zv);
    const __half2 a = __hfma2(__hneg2(pi), zi, __hmul2(pr, zr)), b = __hfma2(pi, zr, __hmul2(pr, zi));
    return {*reinterpret_cast<const uint32_t*>(&a), *reinterpret_cast<const uint32_t*>(&b)};
}
__device__ __forceinline__ uint32_t packz(cplx z) { return pack2h(z.r, z.i); }
__device__ __forceinline__ void wgmma_kg(float (&d)[24], uint64_t da, uint64_t db, int scale_d) {
    asm volatile("{\n.reg .pred p;\nsetp.ne.b32 p, %26, 0;\n"
                 "wgmma.mma_async.sync.aligned.m64n48k16.f32.f16.f16 "
                 "{%0,%1,%2,%3,%4,%5,%6,%7,%8,%9,%10,%11,%12,%13,%14,%15,%16,%17,%18,%19,%20,%21,%22,%23}, %24, %25, p, 1, 1, 1, 1;\n}\n"
                 : "+f"(d[0]), "+f"(d[1]), "+f"(d[2]), "+f"(d[3]), "+f"(d[4]), "+f"(d[5]), "+f"(d[6]), "+f"(d[7]), "+f"(d[8]), "+f"(d[9]),
                   "+f"(d[10]), "+f"(d[11]), "+f"(d[12]), "+f"(d[13]), "+f"(d[14]), "+f"(d[15]), "+f"(d[16]), "+f"(d[17]), "+f"(d[18]), "+f"(d[19]),
                   "+f"(d[20]), "+f"(d[21]), "+f"(d[22]), "+f"(d[23])
                 : "l"(da), "l"(db), "r"(scale_d));
}

struct SsmParams { const bf16 *lar, *aim, *cre, *cim, *logdt, *dskip; };
constexpr int KG_TABLES = 6 * 16384, KG_RES = 1664;
struct KgShared { uint32_t kmax[6], kexp[6]; float cinv[6]; };
struct KgParams { uint32_t l[3], a[3], r[3], i[3], dt, ds; };

__device__ __forceinline__ bool kg_is_hi(int warp) { return ((warp >> 1) ^ (warp >> 2)) & 1; }
__device__ __forceinline__ void kgen_load(KgParams& kp, int d0, int warp, int lane, const SsmParams& sp) {
    const int d = d0 + min(2 * (warp >> 2) + (warp & 1), 4), idx = d * (NMODE / 2) + lane;
    const bf16 *pr = kg_is_hi(warp) ? sp.cre : sp.lar, *pi = kg_is_hi(warp) ? sp.cim : sp.aim;
    kp.dt = __ldg((const uint16_t*)sp.logdt + d);
#pragma unroll
    for (int j = 0; j < 3; j++) {
        kp.l[j] = __ldg((const uint32_t*)sp.lar + idx + 32 * j); kp.a[j] = __ldg((const uint32_t*)sp.aim + idx + 32 * j);
        kp.r[j] = __ldg((const uint32_t*)pr + idx + 32 * j); kp.i[j] = __ldg((const uint32_t*)pi + idx + 32 * j);
    }
    kp.ds = __ldg((const uint16_t*)sp.dskip + d0 + min(warp >> 1, 4));
}

struct KgAnchors { uint32_t v[8]; };
__device__ __forceinline__ KgAnchors kg_anchor_lo(const KgParams& kp, uint32_t sel, float dt) {
    auto B = [&](uint32_t v) { return __uint_as_float(__byte_perm(v, 0u, sel)); };
    const float arl = -rbf(ex2(B(kp.l[0]) * 1.4426950408889634f)) * dt * 1.4426950408889634f, ai = B(kp.a[0]) * dt;
    const cplx z8 = cexp_p(arl, ai, 8.f), z16 = csq(z8), z24 = cmul(z16, z8), z32 = csq(z16), z64 = csq(z32), z128 = csq(z64), z192 = cmul(z128, z64);
    return {{pack2h(1.f, z8.r), pack2h(0.f, z8.i), pack2h(z16.r, z24.r), pack2h(z16.i, z24.i), packz(z32), packz(z64), packz(z128), packz(z192)}};
}
__device__ __forceinline__ KgAnchors kg_anchor_hi(const KgParams& kp, uint32_t sel, float dt, float cs) {
    auto B = [&](uint32_t v) { return __uint_as_float(__byte_perm(v, 0u, sel)); };
    const float arl = -rbf(ex2(B(kp.l[0]) * 1.4426950408889634f)) * dt * 1.4426950408889634f, ai = B(kp.a[0]) * dt;
    const cplx z1 = cexp_p(arl, -ai, 1.f), z2 = csq(z1), z4 = csq(z2), z256 = cexp_p(arl, -ai, 256.f), z512 = csq(z256), z1024 = csq(z512);
    const cplx H0 = {B(kp.r[0]) * cs, -B(kp.i[0]) * cs}, H4 = cmul(H0, z4);
    return {{pack2h(H0.r, H4.r), pack2h(H0.i, H4.i), packz(z1), packz(z2), packz(z256), packz(z512), packz(z1024), 0u}};
}

__device__ __forceinline__ void kgen_tables(KgParams& kp, uint32_t scr, uint32_t dump, KgShared* ks, int warp, int lane TS_ARG) {
    const int wg = warp >> 2, half = warp & 1, sw = lane & 7;
    const bool hi = kg_is_hi(warp);
    TS(23);
    const float dt = rbf(ex2(bf_lo(kp.dt) * 1.4426950408889634f));
    uint32_t sel = (wg == 2 && half) ? 0x3244u : 0x1044u;
    float cs = 0.f;
    KgAnchors an;
    if (hi) {
        uint32_t m = 0;
#pragma unroll
        for (int j = 0; j < 3; j++) m = __vmaxu2(m, __vmaxu2(kp.r[j] & 0x7FFF7FFFu, kp.i[j] & 0x7FFF7FFFu));
        m = __reduce_max_sync(~0u, max(m << 16, m & 0xFFFF0000u));
        const uint32_t e = min(max(__float_as_uint(2.f * dt * __uint_as_float(m)) >> 23, 2u), 252u);
        cs = 2.f * dt * __uint_as_float((253u - e) << 23);
        if (lane == 0) { ks->cinv[2 * wg + half] = __uint_as_float((e + 1u) << 23); ks->kmax[2 * wg + half] = 0u; }
        an = kg_anchor_hi(kp, sel, dt, cs);
    } else {
        an = kg_anchor_lo(kp, sel, dt);
    }
    float acc[24];
#pragma unroll
    for (int i = 0; i < 24; i++) acc[i] = 0.f;
    uint32_t tb = scr + 2 * wg * 16384 + lane * 128;
    uint64_t da = mkdesc(scr + 2 * wg * 16384, 4096, 1024, 1);
    int flip = 16384;
#pragma unroll 1
    for (int c = wg == 2 ? 1 : 0, step = wg == 2 ? 2 : 1; c < 6; c += step) {
        if (wg < 2) sel ^= 0x2200u;
        if (!hi) {
            if (c & 1) { kp.l[0] = kp.l[1]; kp.l[1] = kp.l[2]; kp.a[0] = kp.a[1]; kp.a[1] = kp.a[2]; }
            cpair p[4];
            p[0] = {an.v[0], an.v[1]}; p[1] = {an.v[2], an.v[3]};
            p[2] = pmul(p[0], an.v[4]); p[3] = pmul(p[1], an.v[4]);
#pragma unroll
            for (int j = 0; j < 4; j++) {
                cpair v[4];
#pragma unroll
                for (int i = 0; i < 4; i++) v[i] = j ? pmul(p[i], an.v[4 + j]) : p[i];
                const uint32_t a = tb + (((4 * half + j) ^ sw) << 4);
                sts128(a, make_uint4(v[0].r, v[1].r, v[2].r, v[3].r));
                sts128(a + 4096, make_uint4(v[0].i, v[1].i, v[2].i, v[3].i));
            }
            an = kg_anchor_lo(kp, sel, dt);
        } else {
            if (c & 1) {
#pragma unroll
                for (int j = 0; j < 2; j++) { kp.l[j] = kp.l[j + 1]; kp.a[j] = kp.a[j + 1]; kp.r[j] = kp.r[j + 1]; kp.i[j] = kp.i[j + 1]; }
            }
            const uint32_t h1 = an.v[2], h2 = an.v[3], h256 = an.v[4], h512 = an.v[5], h1024 = an.v[6];
            cpair p[11];
            p[0] = {an.v[0], an.v[1]};
            p[1] = pmul(p[0], h2); p[2] = pmul(p[0], h1); p[3] = pmul(p[1], h1);
            p[4] = pmul(p[0], h256); p[5] = pmul(p[1], h256); p[6] = pmul(p[0], h512); p[7] = pmul(p[4], h512);
            p[8] = pmul({__byte_perm(p[0].r, p[4].r, 0x5410), __byte_perm(p[0].i, p[4].i, 0x5410)}, h1024);
            p[9] = pmul(p[8], h512); p[10] = pmul(p[8], h1024);
#pragma unroll
            for (int j = 0; j < 3; j++) {
                const uint32_t a = tb + 8192 + (((3 * half + j) ^ sw) << 4);
                sts128(a, make_uint4(p[4 * j].r, p[4 * j + 1].r, p[4 * j + 2].r, p[j < 2 ? 4 * j + 3 : 10].r));
                sts128(a + 4096, make_uint4(p[4 * j].i, p[4 * j + 1].i, p[4 * j + 2].i, p[j < 2 ? 4 * j + 3 : 10].i));
            }
            an = kg_anchor_hi(kp, sel, dt, cs);
        }
        if (c == 0) TS(24);
        if (c == 3) TS(25);
        fence_async_smem();
        wg_wait<0>();
        named_bar(5 + wg, 128);
        wg_fence();
#pragma unroll
        for (int k = 0; k < 4; k++) wgmma_kg(acc, da + k * 128, da + 512 + k * 128, 1);
        wg_commit();
        tb += flip; da += flip >> 4; flip = -flip;
    }
    const bool up = warp & 2;
    const int r = 2 * wg + up, lo0 = 16 * half + (lane >> 2);
    const uint32_t o = dump + r * KG_RES + lo0 * 52 + 4 * (lane & 3);
    const float ci = __uint_as_float(lds32(s2u(&ks->cinv[r])));
    const float ds = (lane == 0 && warp <= 8 && !half) ? bf_lo(kp.ds) : 0.f;
    TS(26);
    wg_wait<0>();
    float v[12], m = 0.f;
#pragma unroll
    for (int j = 0; j < 12; j++) { v[j] = fmaf(ci, up ? acc[12 + j] : acc[j], j ? 0.f : ds); m = fmaxf(m, fabsf(v[j])); }
    const uint32_t mm = __reduce_max_sync(~0u, __float_as_uint(m));
    if (lane == 0) asm volatile("red.shared.max.u32 [%0], %1;" ::"r"(s2u(&ks->kmax[r])), "r"(mm) : "memory");
    named_bar(5 + wg, 128);
    const float mx = __uint_as_float(lds32(s2u(&ks->kmax[r]))) + (wg == 2 ? __uint_as_float(lds32(s2u(&ks->kmax[r ^ 1]))) : 0.f);
    const uint32_t e = min(max(__float_as_uint(mx) >> 23, 4u), 250u);
    const float sc = __uint_as_float((253u - e) << 23);
    if (lane == 0) ks->kexp[r] = e;
#pragma unroll
    for (int j = 0; j < 6; j++) sts32(o + (j & 1) * 416 + (j >> 1) * 16, pack2h(v[2 * j] * sc, v[2 * j + 1] * sc));
}
#define F_PPOS 0
#define F_STAG 4
__device__ __forceinline__ void wgmma_h64_rs(uint32_t (&d)[16], const uint4& a, uint64_t db, int scale_d) {
    asm volatile("{\n.reg .pred p;\nsetp.ne.b32 p, %21, 0;\n"
                 "wgmma.mma_async.sync.aligned.m64n64k16.f16.f16.f16 {%0,%1,%2,%3,%4,%5,%6,%7,%8,%9,%10,%11,%12,%13,%14,%15}, {%16,%17,%18,%19}, %20, p, 1, 1, 1;\n}\n"
                 : "+r"(d[0]), "+r"(d[1]), "+r"(d[2]), "+r"(d[3]), "+r"(d[4]), "+r"(d[5]), "+r"(d[6]), "+r"(d[7]), "+r"(d[8]), "+r"(d[9]),
                   "+r"(d[10]), "+r"(d[11]), "+r"(d[12]), "+r"(d[13]), "+r"(d[14]), "+r"(d[15])
                 : "r"(a.x), "r"(a.y), "r"(a.z), "r"(a.w), "l"(db), "r"(scale_d));
}
template <int TB>
__device__ __forceinline__ void wgmma_h32_rs(uint32_t (&d)[8], const uint4& a, uint64_t db, int scale_d) {
    asm volatile("{\n.reg .pred p;\nsetp.ne.b32 p, %13, 0;\n"
                 "wgmma.mma_async.sync.aligned.m64n32k16.f16.f16.f16 {%0,%1,%2,%3,%4,%5,%6,%7}, {%8,%9,%10,%11}, %12, p, 1, 1, %14;\n}\n"
                 : "+r"(d[0]), "+r"(d[1]), "+r"(d[2]), "+r"(d[3]), "+r"(d[4]), "+r"(d[5]), "+r"(d[6]), "+r"(d[7])
                 : "r"(a.x), "r"(a.y), "r"(a.z), "r"(a.w), "l"(db), "r"(scale_d), "n"(TB));
}
__device__ __forceinline__ void wgmma_s1(uint32_t (&d)[16], const uint4& a, uint64_t db, int scale_d) { wgmma_h64_rs(d, a, db, scale_d); }
__device__ __forceinline__ void wgmma_s1(uint32_t (&d)[8], const uint4& a, uint64_t db, int scale_d) { wgmma_h32_rs<1>(d, a, db, scale_d); }
__device__ __forceinline__ void wgmma_s4(float (&d)[32], const uint4& a, uint64_t db, uint32_t meta, int scale_d) {
    asm volatile("{\n.reg .pred p;\nsetp.ne.b32 p, %38, 0;\n"
                 "wgmma.mma_async.sp.sync.aligned.m64n64k32.f32.f16.f16 {%0,%1,%2,%3,%4,%5,%6,%7,%8,%9,%10,%11,%12,%13,%14,%15,%16,%17,%18,%19,%20,%21,%22,%23,%24,%25,%26,%27,%28,%29,%30,%31}, {%32,%33,%34,%35}, %36, %37, 0, p, 1, 1, 1;\n}\n"
                 : "+f"(d[0]), "+f"(d[1]), "+f"(d[2]), "+f"(d[3]), "+f"(d[4]), "+f"(d[5]), "+f"(d[6]), "+f"(d[7]), "+f"(d[8]), "+f"(d[9]), "+f"(d[10]), "+f"(d[11]), "+f"(d[12]), "+f"(d[13]), "+f"(d[14]), "+f"(d[15]), "+f"(d[16]), "+f"(d[17]), "+f"(d[18]), "+f"(d[19]), "+f"(d[20]), "+f"(d[21]), "+f"(d[22]), "+f"(d[23]), "+f"(d[24]), "+f"(d[25]), "+f"(d[26]), "+f"(d[27]), "+f"(d[28]), "+f"(d[29]), "+f"(d[30]), "+f"(d[31])
                 : "r"(a.x), "r"(a.y), "r"(a.z), "r"(a.w), "l"(db), "r"(meta), "r"(scale_d));
}
__device__ __forceinline__ void wgmma_s4(float (&d)[16], const uint4& a, uint64_t db, uint32_t meta, int scale_d) {
    asm volatile("{\n.reg .pred p;\nsetp.ne.b32 p, %22, 0;\n"
                 "wgmma.mma_async.sp.sync.aligned.m64n32k32.f32.f16.f16 {%0,%1,%2,%3,%4,%5,%6,%7,%8,%9,%10,%11,%12,%13,%14,%15}, {%16,%17,%18,%19}, %20, %21, 0, p, 1, 1, 1;\n}\n"
                 : "+f"(d[0]), "+f"(d[1]), "+f"(d[2]), "+f"(d[3]), "+f"(d[4]), "+f"(d[5]), "+f"(d[6]), "+f"(d[7]), "+f"(d[8]), "+f"(d[9]), "+f"(d[10]), "+f"(d[11]), "+f"(d[12]), "+f"(d[13]), "+f"(d[14]), "+f"(d[15])
                 : "r"(a.x), "r"(a.y), "r"(a.z), "r"(a.w), "l"(db), "r"(meta), "r"(scale_d));
}

__device__ __forceinline__ uint32_t& u4r(uint4& v, int i) { return i == 0 ? v.x : i == 1 ? v.y : i == 2 ? v.z : v.w; }

template <int NC>
__device__ __forceinline__ void fft_stage(const uint32_t (&u)[2][4], int c, uint32_t eo, int w, int lane) {
    const int mi = lane >> 3, mj = lane & 7;
    const uint32_t a = eo + (8 * w + mj) * 128 + (((4 * c + mi) ^ mj) << 4);
    stsm_x4(a, hadd(u[0][0], u[1][0]), hadd(u[0][1], u[1][1]), hadd(u[0][2], u[1][2]), hadd(u[0][3], u[1][3]));
    stsm_x4(NC == 2 ? a + 4096 : a ^ 64, hsub(u[0][0], u[1][0]), hsub(u[0][1], u[1][1]), hsub(u[0][2], u[1][2]), hsub(u[0][3], u[1][3]));
}
template <int NC>
__device__ __forceinline__ void kernel_stage(const uint4 (&ko)[2], uint32_t kt, uint32_t eo, int w, int lane) {
    uint32_t u[2][2][4];
#pragma unroll
    for (int h = 0; h < 2; h++)
#pragma unroll
        for (int j = 0; j < 4; j++) {
            const uint32_t a0 = kt + (u4(ko[h], j) & 0xFFFF), a1 = kt + (u4(ko[h], j) >> 16);
#pragma unroll
            for (int c = 0; c < 2; c++)
                asm volatile("{\n.reg .b16 a, b;\nld.shared.b16 a, [%1];\nld.shared.b16 b, [%2];\nmov.b32 %0, {a, b};\n}"
                             : "=r"(u[c][h][j]) : "r"(a0 + c * KG_RES), "r"(a1 + c * KG_RES) : "memory");
            if (NC == 1) u[0][h][j] = hadd(u[0][h][j], u[1][h][j]);
        }
#pragma unroll
    for (int c = 0; c < NC; c++) fft_stage<NC>(u[c], c, eo, w, lane);
}

template <int NC, bool SHEAR, class Mid>
__device__ __forceinline__ void fft_forward(const uint4 (&a1)[4], const uint4 (&tw)[4], uint32_t eo, uint32_t s2, uint32_t (&X)[NC][2][8], Mid mid) {
    uint32_t dr[8 * NC], di[8 * NC];
    const uint64_t de = mkdesc(eo, 4096, 1024, 1), d2 = mkdesc(s2, 16, 1024, 1);
    wg_fence();
    wgmma_s1(dr, a1[0], de, 0);
    wgmma_s1(di, a1[2], de + (NC == 2 ? 256 : 4), 0);
    wgmma_s1(dr, a1[1], de + 128, 1);
    wgmma_s1(di, a1[3], de + (NC == 2 ? 384 : 132), 1);
    wg_commit();
    mid();
    wg_wait<0>();
#pragma unroll
    for (int c = 0; c < NC; c++) {
        uint4 zr[2], zi[2];
#pragma unroll
        for (int p = 0; p < 2; p++)
#pragma unroll
            for (int i = 0; i < 4; i++) {
                const uint32_t r = dr[8 * c + 4 * p + i], m = di[8 * c + 4 * p + i], tr = u4(tw[p], i), ti = u4(tw[2 + p], i);
                if (SHEAR) {
                    const uint32_t r1 = hfma(tr, m, r), m1 = hfma(ti, r1, m);
                    u4r(zr[p], i) = hfma(tr, m1, r1); u4r(zi[p], i) = m1;
                } else {
                    u4r(zr[p], i) = hfms(m, ti, hmul(r, tr));
                    u4r(zi[p], i) = hfma(m, tr, hmul(r, ti));
                }
            }
        wg_fence();
        wgmma_h32_rs<0>(X[c][0], zi[0], d2 + 2, 0);
        wgmma_h32_rs<0>(X[c][1], zi[1], d2 + 6, 0);
        wgmma_h32_rs<0>(X[c][0], zr[0], d2, 1);
        wgmma_h32_rs<0>(X[c][1], zr[1], d2 + 4, 1);
        wg_commit();
    }
}

template <int NC, class Idle, class Ready, class Staged>
__device__ __forceinline__ void conv_wg(int ch0, int layer, uint32_t eo, uint32_t zb, uint32_t s23, uint32_t kexp, uint32_t epoch, uint32_t st, uint32_t sbar,
                                        int warp, int lane, uint4 (&a1)[4], uint4 (&tw)[4], Idle idle, Ready ready, Staged staged TS_ARG) {
    const int wg = warp >> 2, w = warp & 3, t = 32 * w + lane, g = lane >> 2, q = lane & 3, mi = lane >> 3, mj = lane & 7;
    auto F = [](uint32_t x) { return __uint_as_float(x); };
    uint32_t KH[NC][2][8];
    TS(2);
    fft_forward<NC, false>(a1, tw, eo, s23, KH, [] {});
    named_bar(1 + wg, 128);
    uint4 a4[4];
#pragma unroll
    for (int i = 0; i < 4; i++) { tw[i] = ldg_tab(4 + i, t); if (NC == 2) a4[i] = ldg_tab(12 + i, t); }
    wg_wait<0>();
    TS(4);
    idle();
    uint2 x[NC][2][2];
    const int ra[2] = {16 * (8 * w + g) + 4 * q, 16 * (63 - 8 * w - g) + 4 * q};
    if (NC == 1) {
        uint4 s[8];
        TS(1);
#pragma unroll
        for (int i = 0; i < 8; i++) s[i] = make_uint4(layer, 0, 0, 0);
        int spin = 0;
        uint32_t bad;
        do {
            bad = 0;
#pragma unroll
            for (int i = 0; i < 8; i++)
                if (((s[i].x ^ layer) & 1u) == 0) s[i] = ld_ll4((const uint4*)(g_fs[(ch0 / 10) & (S_REP - 1)][i & 1] + 1024 * ((i >> 1) & 1) + ra[i >> 2]));
#pragma unroll
            for (int i = 0; i < 8; i++) bad |= ~(s[i].x ^ layer);
        } while ((bad & 1u) && ++spin < (1 << 18));
#pragma unroll
        for (int i = 0; i < 8; i++) sts128(st + i * 2048 + t * 16, s[i]);
        __syncwarp();
        if (lane == 0) mbar_arrive(sbar + 8 * w);
#pragma unroll
        for (int i = 0; i < 4; i++) a4[i] = ldg_tab(12 + i, t);
        TS(14);
    }
    ready();
    TS(5);
    auto xload = [&](int i) {
        const unsigned long long v = ld_ll((const unsigned long long*)(g_x1T + (size_t)(ch0 + (i >> 2)) * XP + 1024 * (i & 1) + ra[(i >> 1) & 1]));
        x[i >> 2][(i >> 1) & 1][i & 1] = make_uint2((uint32_t)v, (uint32_t)(v >> 32));
    };
#pragma unroll
    for (int i = 0; i < 4 * NC; i++) xload(i);
    if (F_PPOS == 0) staged();
    TS(6);
    for (int spin = 0; spin < (1 << 18); spin++) {
        uint32_t bad = 0;
#pragma unroll
        for (int i = 0; i < 4 * NC; i++) bad |= ~(x[i >> 2][(i >> 1) & 1][i & 1].x ^ layer);
        if (!(bad & 1u)) break;
#pragma unroll
        for (int i = 0; i < 4 * NC; i++) if (((x[i >> 2][(i >> 1) & 1][i & 1].x ^ layer) & 1u) == 0) xload(i);
    }
    __syncwarp();
    TS(26);
    if (NC == 2) mbar_wait(sbar + 8 * w, 0);
    {
        uint4 s[2][2][2];
        uint32_t u[NC][2][4];
#pragma unroll
        for (int h = 0; h < 2; h++) {
            if (NC == 1 || h == 0) {
#pragma unroll
                for (int i = 4 * h; i < (NC == 1 ? 4 * h + 4 : 8); i++) s[i >> 2][(i >> 1) & 1][i & 1] = lds128(st + i * 2048 + t * 16);
            }
            if (h == 0) TS(7);
#pragma unroll
            for (int c = 0; c < NC; c++)
#pragma unroll
                for (int j = 0; j < 4; j++) {
                    const uint4 &a = s[h][j >> 1][0], &b = s[h][j >> 1][1];
                    const uint32_t xv = (j & 1) ? x[c][h][j >> 1].y : x[c][h][j >> 1].x;
                    u[c][h][j] = pack2h(fmaf(bf_lo(xv), F(u4(a, 2 * (j & 1))), F(u4(b, 2 * (j & 1)))), fmaf(bf_hi(xv), F(u4(a, 2 * (j & 1) + 1)), F(u4(b, 2 * (j & 1) + 1))));
                }
        }
#pragma unroll
        for (int c = 0; c < NC; c++) fft_stage<NC>(u[c], c, eo, w, lane);
    }
    TS(8);
    fence_async_smem();
    TS(9);
    if (F_PPOS == 1) staged();
    named_bar(1 + wg, 128);
    uint32_t X[NC][2][8], Y[NC][2][8];
    fft_forward<NC, true>(a1, tw, eo, s23, X, [&] { TS(3); if (F_PPOS == 2) staged(); if (F_STAG >= 2 && NC == 2 && wg == 1) named_bar(10 + w, 64); });
    if (F_STAG == 2 && NC == 2 && wg == 0) asm volatile("bar.arrive %0, 64;" ::"r"(10 + w) : "memory");
    TS(10);
    const uint64_t d3 = mkdesc(s23 + 4096, 16, 1024, 1);
#pragma unroll
    for (int c = 0; c < NC; c++) {
        wg_wait<NC - 1>();
        TS(11 + c);
        uint4 pr[2], pi[2];
#pragma unroll
        for (int i = 0; i < 4; i++) {
            const uint32_t er = X[c][0][i], ei = X[c][0][4 + i], orr = X[c][1][i], oi = X[c][1][4 + i];
            const uint32_t ar = KH[c][0][i], ai = KH[c][0][4 + i], br = KH[c][1][i], bi = KH[c][1][4 + i];
            u4r(pr[0], i) = hfms(bi, oi, hfma(br, orr, hfms(ai, ei, hmul(ar, er))));
            u4r(pi[0], i) = hfma(bi, orr, hfma(br, oi, hfma(ai, er, hmul(ar, ei))));
            u4r(pr[1], i) = hfms(ai, oi, hfma(ar, orr, hfms(bi, ei, hmul(br, er))));
            u4r(pi[1], i) = hfma(ai, orr, hfma(ar, oi, hfma(bi, er, hmul(br, ei))));
        }
        if (F_STAG == 3 + c && NC == 2 && wg == 0) asm volatile("bar.arrive %0, 64;" ::"r"(10 + w), "r"(pr[0].x ^ pr[1].w ^ pi[0].y ^ pi[1].z) : "memory");
        wg_fence();
        wgmma_h32_rs<0>(Y[c][0], pr[0], d3, 0);
        wgmma_h32_rs<0>(Y[c][1], pr[1], d3 + 4, 0);
        wgmma_h32_rs<0>(Y[c][0], pi[0], d3 + 2, 1);
        wgmma_h32_rs<0>(Y[c][1], pi[1], d3 + 6, 1);
        wg_commit();
    }
#pragma unroll
    for (int c = 0; c < NC; c++) {
        if (c + 1 < NC) wg_wait<1>(); else wg_wait<0>();
        TS(13 + c);
        uint32_t zr[2][4], zi[2][4];
#pragma unroll
        for (int p = 0; p < 2; p++)
#pragma unroll
            for (int i = 0; i < 4; i++) {
                const uint32_t r = Y[c][p][i], m = Y[c][p][4 + i], tr = u4(tw[p], i), ti = u4(tw[2 + p], i);
                const uint32_t r1 = hfms(tr, m, r), m1 = hfms(ti, r1, m);
                zr[i & 1][2 * p + (i >> 1)] = hfms(tr, m1, r1);
                zi[i & 1][2 * p + (i >> 1)] = m1;
            }
        const int kr = 4 * (mj >> 1) + (mj & 1) + 2 * (mj >> 2), ki = kr ^ 2;
#pragma unroll
        for (int h = 0; h < 2; h++) {
            const uint32_t a = zb + (2 * w + h) * 2048;
            stsm_x4(a + ki * 128 + (((4 * c + mi) ^ (ki & 7)) << 4), zi[h][0], zi[h][1], zi[h][2], zi[h][3]);
            stsm_x4(a + kr * 128 + (((4 * c + mi) ^ (kr & 7)) << 4), zr[h][0], zr[h][1], zr[h][2], zr[h][3]);
        }
    }
    TS(15);
    fence_async_smem();
    TS(16);
    named_bar(1 + wg, 128);
    TS(17);
    float acc[16 * NC];
    const uint64_t dz = mkdesc(zb, 4096, 1024, 1);
    wg_fence();
#pragma unroll
    for (int ks = 0; ks < 4; ks++) wgmma_s4(acc, a4[ks], dz + ks * 256, 0x44EEEE44u, ks > 0);
    wg_commit();
    uint32_t oscale[NC];
#pragma unroll
    for (int c = 0; c < NC; c++) oscale[c] = (lds32(kexp + 4 * c) + 3u) * 0x00800080u;
    const uint32_t fb = ~lds32(epoch) & 1u, keep = layer ? 0u : ~0u;
    wg_wait<0>();
    TS(18);
#pragma unroll
    for (int c = 0; c < NC; c++) {
        uint32_t r[2][4];
#pragma unroll
        for (int j = 0; j < 4; j++) {
            const float* d = acc + 4 * (4 * c + j);
            const uint32_t y0 = pack2(d[0] + d[2], d[1] + d[3]), y1 = pack2(d[0] - d[2], d[1] - d[3]);
            asm("fma.rn.bf16x2 %0, %1, %2, %3;" : "=r"(r[0][j]) : "r"(y0), "r"(oscale[c]), "r"(keep & ((j & 1) ? x[c][0][j >> 1].y : x[c][0][j >> 1].x)));
            asm("fma.rn.bf16x2 %0, %1, %2, %3;" : "=r"(r[1][j]) : "r"(y1), "r"(oscale[c]), "r"(keep & ((j & 1) ? x[c][1][j >> 1].y : x[c][1][j >> 1].x)));
        }
#pragma unroll
        for (int h = 0; h < 2; h++) {
            if (layer == 0) {
                bf16* dst = g_x2T + (size_t)(ch0 + c) * XP + ra[h];
                *(uint2*)dst = make_uint2(r[h][0], r[h][1]);
                *(uint2*)(dst + 1024) = make_uint2(r[h][2], r[h][3]);
            } else {
                st_ll4(&g_of[ch0 / 80][ra[h] >> 6][(ch0 % 80 + c) * 16 + ((ra[h] >> 2) & 15)], (r[h][0] & ~1u) | fb, r[h][1], r[h][2], r[h][3]);
            }
        }
    }
    TS(19);
}

#define Q_SCHED 3
#define Q_WAITFOR(it) (Q_SCHED == 0 ? (it) - 2 : Q_SCHED == 1 ? ((it) == 3 ? 1 : 0) : Q_SCHED == 2 ? -1 : (it) - 1)
#define Q_S0 8
#define A_HPOS 1
#define A_CSPRE 2
#define R_CONS 192
#define F_PRE 4
#define T_PF 1
#define K_CSUN 1
constexpr int K_CSU = K_CSUN;
#define G_MAP 1
#define O_TPOS 5
#define O_PASS 0
#define O_DEPTH 3
#define Q_SP 2
#define X_HINT 1
#define S_FIRST 1
#define S_GATE 1
constexpr int Q_ST = 4;
constexpr int Q_AB = 16384, Q_BB = 30720, Q_SB = Q_AB + Q_BB;
constexpr int Q_EROW = 336;
constexpr int Q_ESLOT = 8 * Q_EROW;
constexpr int Q_EOFF = Q_ST * Q_SB;
constexpr int Q_KG = 2 * Q_SB;
static_assert(3 * Q_ESLOT <= 8192 && Q_KG + KG_TABLES <= Q_EOFF + 4096, "exchange slots, kernel generation");
constexpr int F_EO = Q_EOFF, F_S23 = F_EO + 2 * 8192 + 4096, Q_KDUMP = F_S23 + 8192;
constexpr int Q_SMEM = Q_KDUMP + 6 * KG_RES + TS_SMEM;
__host__ __device__ constexpr int w_grp(int j) { return j < 7 ? 2 * Q_SB + j * 12800 : 0; }
constexpr int W_RES = Q_AB, W_OUT = Q_SB + Q_AB;

constexpr int Q_WOT = Q_EOFF + 4096;

__device__ unsigned g_epoch;
__device__ __align__(1024) unsigned g_bar[4][16][32];
__device__ __align__(1024) uint4 g_wop[8][80][10][8];
__device__ __align__(1024) uint4 g_csp[8][16][96];
__device__ __align__(1024) uint4 g_stp[16][8][64];
__device__ __align__(1024) uint4 g_sp2[16][8][8][8];
__device__ __align__(1024) uint4 g_halo[128][2][5][32];

struct Bars { uint64_t full[Q_ST], empty[Q_ST], wfull[3], ex[7], res, go, qdone, prep, ardy, hdone, fdone, idx, att1, pass, wfree, staged[2], st[4], kfree; };
constexpr int NBAR = sizeof(Bars) / 8;
__host__ __device__ constexpr int bar_count(int i) {
#define BAR_IS(f) (i == offsetof(Bars, f) / 8)
    return (i >= 4 && i < 8) ? 16 : (BAR_IS(go) || (i >= offsetof(Bars, att1) / 8 && i < offsetof(Bars, st) / 8)) ? 4 : BAR_IS(qdone) ? 8 : BAR_IS(prep) ? 96 :
           BAR_IS(hdone) ? 6 : BAR_IS(fdone) ? 3 : BAR_IS(kfree) ? 24 : 1;
}
__device__ __forceinline__ void grid_wait(const unsigned* c, int n, unsigned target, int lane) {
    const unsigned* p = c + 32 * min(lane, n - 1);
    unsigned v;
    int spin = 0;
    do { asm volatile("ld.relaxed.gpu.global.u32 %0, [%1];" : "=r"(v) : "l"(p) : "memory"); } while (!__all_sync(~0u, (int)(v - target) >= 0) && ++spin < (1 << 18));
    fence_acquire();
}
__device__ __forceinline__ void grid_arrive(unsigned* c) {
    fence_release();
    asm volatile("red.relaxed.gpu.global.add.u32 [%0], 1;" ::"l"(c) : "memory");
}

#define TMAP(n) ([] { const CUtensorMap* p_; asm volatile("{\n.reg .b64 t;\nmov.b64 t, fused_kernel_param_" #n ";\ncvta.param.u64 %0, t;\n}" : "=l"(p_)); return p_; }())
extern "C" __global__ void __launch_bounds__(384, 1)
fused_kernel(const SsmParams sp, const __grid_constant__ CUtensorMap mX0, const __grid_constant__ CUtensorMap mX1, const __grid_constant__ CUtensorMap mW,
             const __grid_constant__ CUtensorMap mWr,
             const __grid_constant__ CUtensorMap mRes0, const __grid_constant__ CUtensorMap mRes1, const __grid_constant__ CUtensorMap mOut,
             const __grid_constant__ CUtensorMap mWo, const __grid_constant__ CUtensorMap mFin, const __grid_constant__ CUtensorMap mResA) {
    extern __shared__ __align__(1024) char smraw[];
    __shared__ __align__(8) Bars s_bar[2];
    __shared__ __align__(16) float s_cs[240], s_mean[2][64], s_rstd[2][72];
    __shared__ KgShared s_kg;
    __shared__ uint32_t s_epoch;
    const uint32_t sb = s2u(smraw);
    int tid, warp, lane, bx, rank, blk, hg, rot, c0;
    int role;
    {
        const int c = blockIdx.x >> 1, d = c - 41, r = d >= 21 ? 3 : d >= 14 ? 2 : d >= 7 ? 1 : 0;
        const int gp = c < 4 ? 0 : c <= 40 ? (c + 7) & 7 : d - 7 * r + 1;
        const int k = c < 4 ? c : c <= 40 ? (c >> 3) + (gp == 0 ? 3 : gp >= 3 && gp < 7 ? 0 : -1) : (gp >= 3 ? 5 : 4) + r;
        role = G_MAP == 1 ? 16 * k + 2 * gp + (blockIdx.x & 1) : G_MAP == 2 ? 16 * gp + 2 * k + (blockIdx.x & 1) : blockIdx.x;
    }
    auto indices = [&] {
        asm volatile("mov.u32 %0, %%tid.x;" : "=r"(tid));
        asm volatile("mov.u32 %0, %1;" : "=r"(bx) : "r"(role));
        warp = __shfl_sync(~0u, tid >> 5, 0); lane = tid & 31;
        rank = bx & 1; blk = bx & 15; hg = bx >> 4;
        const int u = ((blk >> 1) + hg) & 7;
        rot = (5 * u) >> 2; c0 = 16 * (u & 3);
    };
    indices();
    TS_DECL;
    TS_BEGIN;
#define EPOCH lds32(s2u(&s_epoch))
    int layer = 0;
    uint32_t bars = s2u(s_bar);
#define BAR(f) (bars + (uint32_t)offsetof(Bars, f))
    auto chunk = [&](int it, int s0) {
        const int i = it < s0 ? it : it - 2;
        return (it >> 1) == (s0 >> 1) ? rot + (it & 1) : i < rot ? i : i + 2;
    };
    auto osrc_of = [&](int j) { return j == 0 ? hg : j - 1 < hg ? j - 1 : j; };
    auto issue_w = [&](uint32_t bb, int it, int lay) {
        const int half = rank;
        const int s = it & (Q_ST - 1);
        const uint32_t fb = bb + 8 * s, db = sb + s * Q_SB + Q_AB + half * 15360;
        const int k0 = chunk(it, Q_SP * lay) * 64 + half * 32;
#pragma unroll
        for (int p = 0; p < 3; p++) tma2d_mc(db + p * 4096, TMAP(3), p * DM + hg * 80, k0, fb, 3);
        tma3d_mc(db + 12288, TMAP(4), hg * 80 + 64, k0, 0, fb, 3);
    };
    auto issue_x = [&](int it) {
        const int s = it & (Q_ST - 1), kc = chunk(it, Q_SP * layer);
        mbar_expect(BAR(full) + 8 * s, Q_SB);
        tma3d(sb + s * Q_SB, TMAP(1) + layer, (layer ? blk : kc) * 64, (layer ? kc : blk) * 64, 0, BAR(full) + 8 * s);
    };
    {
        KgParams kp;
        kgen_load(kp, bx * 5, warp, lane, sp);
        if (warp < 8) {
            cluster_arrive_relaxed();
        } else {
            const int t2 = tid - 256;
            if (elect_one()) {
                if (warp < 10) { prefetch_tmap(TMAP(3)); prefetch_tmap(TMAP(4)); } else prefetch_tmap(warp == 10 ? TMAP(1) : TMAP(8));
                const uint32_t b0 = bars + (warp >= 10 ? sizeof(Bars) : 0);
                if (warp & 1) {
#pragma unroll
                    for (int i = 0; i < NBAR / 2; i++) mbar_init(b0 + i * 8, bar_count(i));
                } else {
#pragma unroll
                    for (int i = NBAR / 2; i < NBAR; i++) mbar_init(b0 + i * 8, bar_count(i));
                }
                fence_mbar_init();
            }
            __syncwarp();
            cluster_arrive_relaxed();
            TS(29);
            const uint32_t epoch0 = ldg32(&g_epoch);
            cluster_wait();
            TS(27);
            if (elect_one()) {
                if (warp < 10) {
                    issue_w(BAR(full), warp - 8, 0);
                } else if (warp == 10) {
                    issue_x(0); issue_x(1);
                    prefetch_l2((const char*)c_fft + bx * (sizeof(c_fft) / 128), sizeof(c_fft) / 128);
                } else {
                    mbar_expect(BAR(idx), 8192 + 6400);
                    asm volatile("cp.async.bulk.tensor.4d.shared::cluster.global.mbarrier::complete_tx::bytes [%0], [%1, {0, 0, %3, %4}], [%2];"
                                 ::"r"(sb + Q_WOT), "l"(TMAP(8)), "r"(BAR(idx)), "r"(10 * hg), "r"(5 * blk) : "memory");
                    bulk_g2s(sb + F_S23, c_fft + 18 * 512, 8192, BAR(idx));
                }
            }
            __syncwarp();
            if (t2 == 0) s_epoch = epoch0;
            TS(30);
        }
        indices();
        kgen_tables(kp, sb + Q_KG, sb + Q_KDUMP, &s_kg, warp, lane TS_PASS);
        if (warp < 8) cluster_wait();
        __syncwarp();
        if (lane == 0) { mbar_arrive_cta(BAR(kfree), 0); mbar_arrive_cta(BAR(kfree), 1); }
        if (warp >= 8) {
            const int t2 = tid - 256;
            float csum[10];
            if (t2 < 64) stg128(&g_sp2[blk][hg][0][0] + t2, make_uint4(0, 0, 0, 0));
            if (t2 >= 128 - 8 * S_REP) stg128((uint4*)g_fs + 8 * S_REP * (bx + 1) + t2 - 128, make_uint4(0, 0, 0, 0));
            if (t2 < 64) stg128(g_x1T + (size_t)(5 * bx + 4) * XP + 64 * (t2 >> 1) + 48 + 8 * (t2 & 1), make_uint4(0, 0, 0, 0));
#pragma unroll
            for (int i = 0; i < 3; i++)
                if (t2 + 128 * i < 320) stg128(&g_halo[bx][0][0][0] + t2 + 128 * i, make_uint4(0, 0, 0, 0));
            if (warp == 8) asm volatile("bar.arrive 13, 128;" ::: "memory"); else named_bar(13, 128);
            if (warp > 8) {
                const int hw = warp - 9, mi = lane >> 3, mj = lane & 7;
                mbar_wait(BAR(idx), 0);
                if (hw == 2 && elect_one()) { bulk_s2g(&g_wop[hg][5 * blk], sb + Q_WOT, 6400); bulk_commit(); }
                __syncwarp();
                mbar_wait(BAR(full), 0);
                mbar_wait(BAR(full) + 8, 0);
#pragma unroll
                for (int f = 0; f < 10; f++) csum[f] = 0.f;
#pragma unroll K_CSU
                for (int G = 0; G < 5; G++) {
                    const int row = c0 + 40 * rank + 8 * G + mj;
                    const uint32_t b = sb + (row >> 6) * Q_SB + Q_AB + ((row >> 5) & 1) * 15360;
                    uint32_t r[10];
                    ldsm_x4_t(r[0], r[1], r[2], r[3], b + hw * 4096 + (row & 31) * 128 + ((mi ^ mj) << 4));
                    ldsm_x4_t(r[4], r[5], r[6], r[7], b + hw * 4096 + (row & 31) * 128 + (((4 + mi) ^ mj) << 4));
                    ldsm_x2_t(r[8], r[9], b + 12288 + hw * 1024 + (row & 31) * 32 + (((mi & 1) ^ (mj >> 2)) << 4));
#pragma unroll
                    for (int f = 0; f < 10; f++) csum[f] += bf_lo(r[f]) + bf_hi(r[f]);
                }
                const int q = lane & 3;
                float t[3];
#pragma unroll
                for (int j = 0; j < 3; j++) {
                    float v[4];
#pragma unroll
                    for (int k = 0; k < 4; k++) v[k] = 4 * j + k < 10 ? csum[4 * j + k] : 0.f;
                    const float a0 = ((q & 2) ? v[2] : v[0]) + __shfl_xor_sync(~0u, (q & 2) ? v[0] : v[2], 2);
                    const float a1 = ((q & 2) ? v[3] : v[1]) + __shfl_xor_sync(~0u, (q & 2) ? v[1] : v[3], 2);
                    t[j] = ((q & 1) ? a1 : a0) + __shfl_xor_sync(~0u, (q & 1) ? a0 : a1, 1);
                }
                st_ll4(&g_csp[hg][blk][tid - 288], ~EPOCH & 1u, __float_as_uint(t[0]), __float_as_uint(t[1]), __float_as_uint(t[2]));
            }
        }
        TS(1);
    }

    uint4 fa1[4], ftw[4];
    auto conv_tables = [&] {
#pragma unroll
        for (int i = 0; i < 4; i++) { fa1[i] = ldg_tab(i, tid & 127); ftw[i] = ldg_tab(8 + i, tid & 127); }
    };
    auto conv_done = [&] {
        if (layer == 0) {
            named_bar(1 + (warp >> 2), 128);
            if ((tid & 127) == 0) {
                mbar_arrive(BAR(fdone));
                grid_arrive(g_bar[2][hg]);
            }
            __syncwarp();
        }
        TS(20);
    };
    if (warp >= 8) {
    asm volatile("setmaxnreg.dec.sync.aligned.u32 %0;" ::"n"(504 - 2 * R_CONS));
#pragma unroll 1
    for (; layer < 2; layer++, bars += sizeof(Bars)) {
        indices();
        TS_PHASE(2 * layer);
        if (warp == 8) {
            if (layer) {
                grid_wait(g_bar[2][0], 8, 48 * (EPOCH + 1), lane);
                mbar_wait(BAR(fdone) - sizeof(Bars), 0);
                fence_async_global();
                TS(1);
            }
            if (elect_one()) {
#pragma unroll 1
                for (int it = layer ? 0 : 2; it < 10; it++) {
                    if (it >= Q_ST) mbar_wait(BAR(empty) + 8 * (it & (Q_ST - 1)), ((it >> 2) - 1) & 1);
                    else if (layer == 0) mbar_wait(BAR(kfree), 0);
                    else if (it > 0 && Q_WAITFOR(it) >= 0) mbar_wait(BAR(full) + 8 * Q_WAITFOR(it), 0);
                    if (it == Q_ST + Q_SP * layer) mbar_wait(BAR(hdone), 0);
                    issue_x(it);
                    if (layer == 0 || it >= F_PRE) issue_w(BAR(full), it, layer);
                }
                if (T_PF) { prefetch_tmap(TMAP(5) + layer); prefetch_tmap(TMAP(7)); prefetch_tmap(TMAP(10)); }
                if (layer == 0) { mbar_wait(BAR(prep), 0); fence_async_global(); }
#pragma unroll 1
                for (int j = 0; j < 8; j++) {
                    const int b = (j + 1) >> 2;
                    const uint32_t fb = BAR(wfull) + 8 * b;
                    if (j == 0 || j == 3 || j == 7) {
                        mbar_wait(BAR(empty) + 8 * ((2 + b) & 3), b < 2);
                        TS(11 + b);
                        mbar_expect(fb, (b == 0 ? 3 : b == 1 ? 4 : 1) * 12800);
                    }
                    bulk_g2s_mc(sb + w_grp(j) + rank * 6400, &g_wop[hg][osrc_of(j) * 10 + rank * 5], 6400, fb, 3);
                }
                mbar_expect(BAR(res), 20480);
                if (layer) {
                    tma3d(sb + W_RES, TMAP(6), blk * 64, hg * 80, 0, BAR(res));
                } else {
#pragma unroll 1
                    for (int p = 0; p < 2; p++) {
                        tma3d(sb + W_RES + p * 10240, TMAP(10), hg * 80, blk * 64, p, BAR(res));
                        tma3d(sb + W_RES + p * 10240 + 8192, TMAP(5), hg * 80 + 64, blk * 64, p, BAR(res));
                    }
                }
            }
            __syncwarp();
        } else {
            const int ht = tid - 288, hw = warp - 9, mi = lane >> 3, mj = lane & 7, g = lane >> 2, q = lane & 3;
            auto F = [](uint32_t x) { return __uint_as_float(x); };
            auto U = [](float x) { return __float_as_uint(x); };
            const uint32_t lb = layer ^ 1, eb = ~EPOCH & 1u;
            mbar_wait(BAR(full) + 8 * Q_SP * layer, 0);
            mbar_wait(BAR(full) + 8 * Q_SP * layer + 8, 0);
            if (ht == 0) TSX(2, 2);
            uint32_t xf[3][20];
#pragma unroll
            for (int i = 0; i < 3; i++) {
                const int tile = min(hw + 3 * i, 7);
#pragma unroll
                for (int k = 0; k < 5; k++) {
                    const int ch = c0 + 16 * k + 8 * (mi >> 1), tok = 16 * (tile & 3) + 8 * (mi & 1);
                    const uint32_t a = sb + ((ch >> 6) + Q_SP * layer) * Q_SB + (tile >> 2) * 8192;
                    if (layer == 0) ldsm_x4(xf[i][4 * k], xf[i][4 * k + 1], xf[i][4 * k + 2], xf[i][4 * k + 3], a + (tok + mj) * 128 + ((((ch & 63) >> 3) ^ mj) << 4));
                    else ldsm_x4_t(xf[i][4 * k], xf[i][4 * k + 1], xf[i][4 * k + 2], xf[i][4 * k + 3], a + ((ch & 63) + mj) * 128 + (((tok >> 3) ^ mj) << 4));
                }
            }
            fence_async_smem();
            __syncwarp();
            if (lane == 0) { mbar_arrive_cta(BAR(hdone), 0); mbar_arrive_cta(BAR(hdone), 1); }
            if (ht == 0) TSX(2, 3);
            if (layer == 0) {
                if (hw == 2 && elect_one()) { bulk_wait(); fence_async_global(); grid_arrive(g_bar[3][hg]); }
                __syncwarp();
                mbar_wait(BAR(kfree), 0);
            }
            if (ht == 0) TSX(2, 8);
#pragma unroll 1
            for (int tile = hw; tile < 8; tile += 3) {
                float a[4] = {0.f, 0.f, 0.f, 0.f};
#pragma unroll
                for (int j = 0; j < 20; j++) {
                    const float lo = bf_lo(xf[0][j]), hi = bf_hi(xf[0][j]);
                    a[2 * (j & 1)] += lo + hi; a[2 * (j & 1) + 1] = fmaf(lo, lo, fmaf(hi, hi, a[2 * (j & 1) + 1]));
                    xf[0][j] = xf[1][j]; xf[1][j] = xf[2][j];
                }
#pragma unroll
                for (int j = 0; j < 4; j++) { a[j] += __shfl_xor_sync(~0u, a[j], 1); a[j] += __shfl_xor_sync(~0u, a[j], 2); }
                if (q == 0) st_ll4(&g_stp[blk][hg][8 * tile + g], (U(a[0]) & ~1u) | lb, U(a[1]), U(a[2]), U(a[3]));
            }
            if (ht == 0) TSX(2, 4);
            if (layer == 0) {
                float t[4] = {0.f, 0.f, 0.f, 0.f};
                uint4 v[16];
                int spin = 0;
                uint32_t bad;
                do {
                    bad = 0;
#pragma unroll
                    for (int j = 0; j < 16; j++) v[j] = ld_ll4(&g_csp[hg][j][ht]);
#pragma unroll
                    for (int j = 0; j < 16; j++) bad |= v[j].x ^ eb;
                } while ((bad & 1u) && ++spin < (1 << 18));
#pragma unroll
                for (int j = 0; j < 16; j++) { t[0] += F(v[j].y); t[1] += F(v[j].z); t[2] += F(v[j].w); }
#pragma unroll
                for (int j = 0; j < 3; j++) if (q + 4 * j < 10) s_cs[80 * hw + 20 * (g >> 1) + 2 * (q + 4 * j) + (g & 1)] = t[j];
                if (hw == 2) grid_wait(g_bar[3][0], 8, 16 * (EPOCH + 1), lane);
            }
            if (ht == 0) TSX(2, 15);
            if (ht < 80) {
                const bool halo = ht >= 64;
                const int p = halo ? (ht >> 3) & 1 : ht >> 5, i = halo ? (ht & 7) - 8 : 8 + 2 * (ht & 24) + (ht & 7);
                const uint4* src = &g_stp[halo && blk ? blk - 1 : blk][0][halo ? 32 * p + 24 + (ht & 7) : ht];
                uint4 v[8];
                int spin = 0;
                uint32_t bad;
                do {
                    bad = 0;
#pragma unroll
                    for (int j = 0; j < 8; j++) v[j] = ld_ll4(src + 64 * j);
#pragma unroll
                    for (int j = 0; j < 8; j++) bad |= v[j].x ^ lb;
                } while ((bad & 1u) && ++spin < (1 << 18));
                float t[4] = {0.f, 0.f, 0.f, 0.f};
#pragma unroll
                for (int j = 0; j < 8; j++) { t[0] += F(v[j].x); t[1] += F(v[j].y); t[2] += F(v[j].z); t[3] += F(v[j].w); }
                const uint32_t s0 = ln_finish_packed(t[0], t[1]), s1 = ln_finish_packed(t[2], t[3]);
                if (!halo) { s_mean[p][i - 8] = bf_hi(s0); s_mean[p][i] = bf_hi(s1); s_rstd[p][i] = frcp(bf_lo(s0)); }
                s_rstd[p][i + 8] = frcp(bf_lo(s1));
            }
            fence_acquire();
            mbar_arrive(BAR(prep));
            if (ht == 0) TSX(2, 5);
        }
        __syncwarp();
        TS_PHASE(2 * layer + 1);
        TS(0);
        indices();
        {
            const uint4 ko[2] = {ldg_tab(16, tid & 127), ldg_tab(17, tid & 127)};
            conv_tables();
            mbar_wait(BAR(att1), 0);
            kernel_stage<1>(ko, sb + Q_KDUMP + 4 * KG_RES, sb + F_EO + 2 * 8192, warp & 3, lane);
            fence_async_smem();
            named_bar(3, 128);
        }
        conv_wg<1>(5 * bx + 4, layer, sb + F_EO + 2 * 8192, sb + 2 * Q_SB, sb + F_S23, s2u(&s_kg.kexp[4]), s2u(&s_epoch), sb + 3 * Q_SB, BAR(st), warp, lane, fa1, ftw,
        [&] {
            if (warp >= 10) {
                const int i = warp - 10;
                mbar_wait(BAR(staged) + 8 * i, 0);
                if (elect_one()) {
                    asm volatile("cp.async.bulk.tensor.2d.global.shared::cta.bulk_group [%0, {%2, %3}], [%1];"
                                 ::"l"(TMAP(7)), "r"(sb + W_OUT + i * 10240), "r"(1024 * i + 64 * blk), "r"(hg * 80) : "memory");
                    bulk_commit();
                    asm volatile("cp.async.bulk.wait_group.read 0;" ::: "memory");
                    if (layer == 0) { mbar_arrive_cta(BAR(wfree), 0); mbar_arrive_cta(BAR(wfree), 1); }
                }
                __syncwarp();
            } else if (warp == 9) {
                auto F = [](uint32_t x) { return __uint_as_float(x); };
                mbar_wait(BAR(staged) + 8 * (hg >> 2), 0);
                TS(23);
                const uint4* src = &g_sp2[blk][hg][0][0] + lane;
                uint4 a, b;
                int spin = 0;
                do { a = ld_ll4(src); b = ld_ll4(src + 32); } while (__any_sync(~0u, ~((a.x ^ layer) & (b.x ^ layer)) & 1u) && ++spin < (1 << 18));
                TS(24);
                const bool up = lane & 8;
                const float s0 = F(a.x) + F(b.x), q0 = F(a.y) + F(b.y), s1 = F(a.z) + F(b.z), q1 = F(a.w) + F(b.w);
                float sm = (up ? s1 : s0) + __shfl_xor_sync(~0u, up ? s0 : s1, 8), sq = (up ? q1 : q0) + __shfl_xor_sync(~0u, up ? q0 : q1, 8);
                sm += __shfl_xor_sync(~0u, sm, 16); sq += __shfl_xor_sync(~0u, sq, 16);
                const float m = sm * (1.0f / DM), r = frsq(fmaxf(fmaf(sq, 1.0f / DM, fmaf(-m, m, 1e-5f)), 1e-5f));
                const uint32_t v = __float_as_uint(lane & 16 ? -m * r : r);
                const uint32_t v0 = __shfl_sync(~0u, v, 4 * lane), v1 = __shfl_sync(~0u, v, 4 * lane + 1), v2 = __shfl_sync(~0u, v, 4 * lane + 2), v3 = __shfl_sync(~0u, v, 4 * lane + 3);
#pragma unroll
                for (int i = 0; i < (S_REP + 3) / 4; i++)
                    if (4 * i + (lane >> 3) < S_REP)
                        st_ll4((uint4*)(g_fs[4 * i + (lane >> 3)][(lane >> 2) & 1] + 1024 * (hg >> 2) + 64 * blk + 16 * (hg & 3)) + (lane & 3), (v0 & ~1u) | (layer ^ 1), v1, v2, v3);
            }
            TS(25);
            if (S_GATE) named_bar(3, 128);
            else { mbar_wait(BAR(staged), 0); mbar_wait(BAR(staged) + 8, 0); }
        }, [&] { mbar_wait(BAR(ardy), 0); }, [&] {
            if (T_PF && tid == 352) prefetch_tmap(layer ? TMAP(9) : TMAP(2));
            if (layer == 0 && warp - 8 < F_PRE && elect_one()) { mbar_wait(BAR(wfree), 0); issue_w(BAR(full) + sizeof(Bars), warp - 8, 1); }
            __syncwarp();
        } TS_PASS);
        conv_done();
    }
    } else {
#pragma unroll 1
    for (; layer < 2; layer++, bars += sizeof(Bars)) {
    indices();
    TS_PHASE(2 * layer);
    const int wg = warp >> 2, w = warp & 3;
    const int mi = lane >> 3, mj = lane & 7, g = lane >> 2, q = lane & 3;
    TS(2);
    float acc[120];
#pragma unroll
    for (int i = 0; i < 120; i++) acc[i] = 0.f;
    auto release = [&](int it) {
        if (lane == 0) { mbar_arrive_cta(BAR(empty) + 8 * (it & (Q_ST - 1)), 0); mbar_arrive_cta(BAR(empty) + 8 * (it & (Q_ST - 1)), 1); }
    };
#pragma unroll 1
    for (int it = 0; it < 10; it++) {
        const int s = it & (Q_ST - 1);
        const uint32_t st = sb + s * Q_SB;
        const bool hold = wg == 1 && it == Q_S0;
        if (hold) {
            wg_wait<0>();
            release(it - 1);
            mbar_wait(BAR(go), 0);
        }
        mbar_wait(BAR(full) + 8 * (s), (it >> 2) & 1);
        if (it < 2) TS(3 + it);
        if (it == 6) TS(5);
        if (it == 9) TS(6);
        const uint64_t da = mkdesc(st + wg * 8192, 16, 1024, 1);
        const uint64_t db = mkdesc(st + Q_AB, 4096, 1024, 1);
        const uint64_t dr = mkdesc(st + Q_AB + 12288, 1024, 256, 3);
        if (layer == 0) {
            wg_fence();
#pragma unroll
            for (int ks = 0; ks < 4; ks++) {
                const int sc = 1;
                wgmma_n192<0, 1>(*(float(*)[96]) & acc[0], da + ks * 2, db + (ks >> 1) * 960 + (ks & 1) * 128, sc);
                wgmma_n48<0, 1>(*(float(*)[24]) & acc[96], da + ks * 2, dr + (ks >> 1) * 960 + (ks & 1) * 32, sc);
            }
            wg_commit();
        } else {
            wg_fence();
#pragma unroll
            for (int ks = 0; ks < 4; ks++) {
                const int sc = 1;
                wgmma_n192<1, 1>(*(float(*)[96]) & acc[0], da + ks * 128, db + (ks >> 1) * 960 + (ks & 1) * 128, sc);
                wgmma_n48<1, 1>(*(float(*)[24]) & acc[96], da + ks * 128, dr + (ks >> 1) * 960 + (ks & 1) * 32, sc);
            }
            wg_commit();
        }
        wg_wait<1>();
        if (it > 0 && !hold) release(it - 1);
    }
    if (wg == 0 && lane == 0) mbar_arrive(BAR(go));
    asm volatile("setmaxnreg.inc.sync.aligned.u32 %0;" ::"n"(R_CONS));
    mbar_wait(BAR(prep), 0);
    const uint32_t ob = layer ^ 1;
    const bool first = (blk == 0 && w == 0);
    const bool sel0 = (2 * q > g), sel1 = (2 * q + 1 > g);
    constexpr float SC = 0.22360679774997896f * 1.4426950408889634f;
    const float m0 = s_mean[wg][16 * w + g], m1 = s_mean[wg][8 + 16 * w + g];
    uint4 cs[3][5];
    auto cs_load = [&](int p) {
#pragma unroll
        for (int i = 0; i < 5; i++) cs[p][i] = lds128(s2u(&s_cs[80 * p + 20 * q + 4 * i]));
    };
    if (A_CSPRE >= 1) cs_load(1);
    if (A_CSPRE >= 2) cs_load(2);
    wg_wait<0>();
    if (A_CSPRE < 1) cs_load(1);
    if (A_CSPRE < 2) cs_load(2);
    TS(7);
    if (lane == 0) mbar_arrive(BAR(qdone));
    uint32_t ql[10], qh[10], kl[10], kh[10], vl[10], vh[10];
    auto fold = [&](int p, int f, int h) {
        const int j = (f < 8) ? 8 * p + f : 24 + 2 * p + (f - 8);
        const float c0 = __uint_as_float(u4(cs[p][f >> 1], 2 * (f & 1))), c1 = __uint_as_float(u4(cs[p][f >> 1], 2 * (f & 1) + 1));
        const float m = h ? m1 : m0;
        return pack2(fmaf(-m, c0, acc[4 * j + 2 * h]), fmaf(-m, c1, acc[4 * j + 2 * h + 1]));
    };
#pragma unroll
    for (int f = 0; f < 10; f++) { kh[f] = fold(1, f, 1); vh[f] = fold(2, f, 1); }
    {
        const uint32_t mk = w == 3 ? 1u : 0u;
        auto mark = [&](uint32_t& v) { v = (v & ~mk) | (ob & mk); };
        mark(kh[0]); mark(kh[5]); mark(vh[0]); mark(vh[4]); mark(vh[8]);
    }
    if (w == 3) {
        uint4* hp = &g_halo[bx][wg][0][lane];
        st_ll4(hp, kh[0], kh[1], kh[3], kh[4]); st_ll4(hp + 32, kh[5], kh[6], kh[8], kh[9]);
        st_ll4(hp + 64, vh[0], vh[1], vh[2], vh[3]); st_ll4(hp + 96, vh[4], vh[5], vh[6], vh[7]);
        st_ll4(hp + 128, vh[8], vh[9], kh[2], kh[7]);
    } else {
        const uint32_t a = sb + Q_EOFF + wg * 8192 + w * Q_ESLOT + mj * Q_EROW + mi * 16;
        stsm_x4(a, kh[0], kh[1], kh[3], kh[4]);
        stsm_x4(a + 64, kh[5], kh[6], kh[8], kh[9]);
        stsm_x4(a + 128, vh[0], vh[1], vh[2], vh[3]);
        stsm_x4(a + 192, vh[4], vh[5], vh[6], vh[7]);
        stsm_x4(a + 256, vh[8], vh[9], kh[2], kh[7]);
        __syncwarp();
        if (lane == 0) mbar_arrive(BAR(ex) + 8 * warp);
    }
    TS(9);
    cs_load(0);
#pragma unroll
    for (int f = 0; f < 10; f++) { kl[f] = fold(1, f, 0); vl[f] = fold(2, f, 0); }
#pragma unroll
    for (int f = 0; f < 10; f++) { ql[f] = fold(0, f, 0); qh[f] = fold(0, f, 1); }
    auto rs = [&](int i) { return __uint_as_float(lds32(s2u(&s_rstd[wg][16 * w + i]))); };
    const float kx0 = rs(2 * q + (sel0 ? 0 : 8)), kx1 = rs(2 * q + (sel1 ? 1 : 9)), ky0 = rs(2 * q + (sel0 ? 8 : 16)), ky1 = rs(2 * q + (sel1 ? 9 : 17));
    const float rx = SC * rs(8 + g), ry = SC * rs(16 + g), cx0 = rx * kx0, cx1 = rx * kx1, cy0 = ry * ky0, cy1 = ry * ky1;
    uint4 hv[5];
    const uint4* hp = &g_halo[bx - 1][wg][0][lane];
    auto prev = [&] {
        if (w > 0) {
            const uint32_t a = sb + Q_EOFF + wg * 8192 + (w - 1) * Q_ESLOT + mj * Q_EROW + mi * 16;
            mbar_wait(BAR(ex) + 8 * (warp - 1), 0);
            ldsm_x4(hv[0].x, hv[0].y, hv[0].z, hv[0].w, a);
            ldsm_x4(hv[1].x, hv[1].y, hv[1].z, hv[1].w, a + 64);
            ldsm_x4_t(hv[2].x, hv[2].y, hv[2].z, hv[2].w, a + 128);
            ldsm_x4_t(hv[3].x, hv[3].y, hv[3].z, hv[3].w, a + 192);
            ldsm_x2_t(hv[4].x, hv[4].y, a + 256);
            ldsm_x2(hv[4].z, hv[4].w, a + 288 - (lane >> 4) * 32);
        } else if (blk > 0) {
#pragma unroll
            for (int f = 0; f < 5; f++) hv[f] = ld_ll4(hp + 32 * f);
        } else {
#pragma unroll
            for (int f = 0; f < 5; f++) hv[f] = make_uint4(0, 0, 0, 0);
        }
    };
    if (A_HPOS == 0) prev();
    uint32_t vt[10][2];
#pragma unroll
    for (int f = 0; f < 10; f++) { vt[f][0] = movm_t(vl[f]); vt[f][1] = movm_t(vh[f]); }
    if (A_HPOS == 1) prev();
    TS(10);
    auto FA = [](int h) { return h == 0 ? 0 : h == 1 ? 3 : h == 2 ? 5 : 8; };
    auto FH = [](int h) { return h < 2 ? 2 : 7; };
    const uint32_t pm = (sel0 ? 0xFFFFu : 0u) | (sel1 ? 0xFFFF0000u : 0u);
    auto softmax = [&](float x0, float x1, float k0, float k1) {
        float mx = fmaxf(x0, x1);
        mx = fmaxf(mx, __shfl_xor_sync(~0u, mx, 1));
        mx = fmaxf(mx, __shfl_xor_sync(~0u, mx, 2));
        x0 = ex2(x0 - mx); x1 = ex2(x1 - mx);
        float sx = x0 + x1;
        sx += __shfl_xor_sync(~0u, sx, 1);
        sx += __shfl_xor_sync(~0u, sx, 2);
        const float ix = frcp(sx);
        return pack2(x0 * k0 * ix, x1 * k1 * ix);
    };
    uint32_t qm[4][2], py[4];
    float sl[4][2];
#pragma unroll
    for (int h = 0; h < 4; h++) {
        const int fa = FA(h), fb = fa + 1, fh = FH(h);
        const bool mine = (h & 1) ? (q >= 2) : (q < 2);
        qm[h][0] = mine ? ql[fh] : 0u; qm[h][1] = mine ? qh[fh] : 0u;
        float S1[4] = {0.f, 0.f, 0.f, 0.f}, S2[4] = {0.f, 0.f, 0.f, 0.f};
        mma16816(S1, ql[fa], qh[fa], ql[fb], qh[fb], kl[fa], kl[fb]); mma1688(S1, qm[h][0], qm[h][1], kl[fh]);
        mma16816(S2, ql[fa], qh[fa], ql[fb], qh[fb], kh[fa], kh[fb]); mma1688(S2, qm[h][0], qm[h][1], kh[fh]);
        sl[h][0] = S1[0]; sl[h][1] = S1[1];
        py[h] = softmax((sel0 ? S1[2] : S2[2]) * cy0, (sel1 ? S1[3] : S2[3]) * cy1, ky0, ky1);
    }
    TS(11);
    if (w == 0 && blk > 0) {
        int spin = 0;
        while (__any_sync(~0u, ((hv[0].x ^ ob) | (hv[1].x ^ ob) | (hv[2].x ^ ob) | (hv[3].x ^ ob) | (hv[4].x ^ ob)) & 1u) && ++spin < (1 << 18)) {
#pragma unroll
            for (int f = 0; f < 5; f++) hv[f] = ld_ll4(hp + 32 * f);
        }
#pragma unroll
        for (int f = 2; f < 4; f++) hv[f] = make_uint4(movm_t(hv[f].x), movm_t(hv[f].y), movm_t(hv[f].z), movm_t(hv[f].w));
        hv[4].x = movm_t(hv[4].x); hv[4].y = movm_t(hv[4].y);
    }
    const uint32_t kp[10] = {hv[0].x, hv[0].y, hv[4].z, hv[0].z, hv[0].w, hv[1].x, hv[1].y, hv[4].w, hv[1].z, hv[1].w};
    const uint32_t vp[10] = {hv[2].x, hv[2].y, hv[2].z, hv[2].w, hv[3].x, hv[3].y, hv[3].z, hv[3].w, hv[4].x, hv[4].y};
    TS(12);
    const uint4 ko[2] = {ldg_tab(16, tid & 127), ldg_tab(17, tid & 127)};
    const float bx0 = first && sel0 ? -INFINITY : 0.f, bx1 = first && sel1 ? -INFINITY : 0.f;
    float oacc[10][4];
#pragma unroll
    for (int h = 0; h < 4; h++) {
        const int fa = FA(h), fb = fa + 1, fh = FH(h);
        const bool mine = (h & 1) ? (q >= 2) : (q < 2);
        float S0[4] = {0.f, 0.f, 0.f, 0.f};
        mma16816(S0, ql[fa], qh[fa], ql[fb], qh[fb], kp[fa], kp[fb]); mma1688(S0, qm[h][0], qm[h][1], kp[fh]);
        const uint32_t px = softmax(fmaf(sel0 ? S0[0] : sl[h][0], cx0, bx0), fmaf(sel1 ? S0[1] : sl[h][1], cx1, bx1), kx0, kx1);
#pragma unroll
        for (int i = 0; i < 3; i++) {
            const int f = (i == 0) ? fa : (i == 1) ? fb : fh;
            float O[4] = {0.f, 0.f, 0.f, 0.f};
            mma16816(O, px & ~pm, py[h] & pm, 0u, py[h] & ~pm, vt[f][0], vt[f][1]);
            mma1688(O, px & pm, 0u, vp[f]);
            if (i < 2 || !(h & 1) || mine) { oacc[f][0] = O[0]; oacc[f][1] = O[1]; oacc[f][2] = O[2]; oacc[f][3] = O[3]; }
        }
    }
    TS(13);
    constexpr int ON = O_DEPTH + 2;
    uint4 of[ON][5];
    const uint32_t fb = (EPOCH ^ ob) & 1u;
    {
        uint4* dst = &g_of[hg][blk][160 * warp + lane];
#pragma unroll
        for (int k = 0; k < 5; k++) {
            of[0][k] = make_uint4((pack2(oacc[2 * k][0], oacc[2 * k][1]) & ~1u) | fb, pack2(oacc[2 * k][2], oacc[2 * k][3]),
                                  pack2(oacc[2 * k + 1][0], oacc[2 * k + 1][1]), pack2(oacc[2 * k + 1][2], oacc[2 * k + 1][3]));
            st_ll4(dst + 32 * k, of[0][k].x, of[0][k].y, of[0][k].z, of[0][k].w);
        }
    }
    if (wg == 1 && lane == 0) mbar_arrive(BAR(att1));
    TS(14);
    float aw[40];
    auto omma = [&](int j) {
        const uint64_t dm = mkdesc(sb + w_grp(j), 1280, 128, 0);
        wg_fence();
#pragma unroll
        for (int k = 0; k < 5; k++) wgmma_rs80(aw, of[j % ON][k], dm + k * 160, j + k > 0);
        wg_commit();
    };
    mbar_wait(BAR(wfull), 0);
    omma(0);
    named_bar(1 + wg, 128);
    kernel_stage<2>(ko, sb + Q_KDUMP + 2 * wg * KG_RES, sb + F_EO + wg * 8192, w, lane);
    TS(8);
    const uint4* osrc = &g_of[0][blk][160 * warp + lane];
    auto oload = [&](int j) {
        const uint4* p = osrc + osrc_of(j) * 20480;
#pragma unroll
        for (int k = 0; k < 5; k++) of[j % ON][k] = ld_ll4(p + 32 * k);
    };
    {
        const uint32_t* pp = &g_of[osrc_of(1 + min(lane, 6))][blk][160 * warp + 159].x;
        uint32_t v;
        int spin = 0;
        do { asm volatile("ld.relaxed.gpu.global.u32 %0, [%1];" : "=r"(v) : "l"(pp) : "memory"); } while (__any_sync(~0u, (v & 1u) != fb) && ++spin < (1 << 18));
    }
    TS(15);
    if (O_PASS && wg == 1) mbar_wait(BAR(pass), 0);
#pragma unroll
    for (int j = 1; j <= O_DEPTH; j++) oload(j);
    TS(16);
#pragma unroll
    for (int j = 1; j < 8; j++) {
        if (j == 3 || j == 7) mbar_wait(BAR(wfull) + 8 * ((j + 1) >> 2), 0);
        const uint4* f = of[j % ON];
        int spin = 0;
        while (__any_sync(~0u, ((f[0].x ^ fb) | (f[1].x ^ fb) | (f[2].x ^ fb) | (f[3].x ^ fb) | (f[4].x ^ fb)) & 1u) && ++spin < (1 << 18)) oload(j);
        if (j + O_DEPTH < 8) { wg_wait<1>(); oload(j + O_DEPTH); }
        if (j == O_PASS && wg == 0 && lane == 0) mbar_arrive(BAR(pass));
        if (j == O_TPOS) { wg_wait<1>(); conv_tables(); }
        if (j == 1) TS(17);
        if (j == 5) TS(18);
        omma(j);
    }
    wg_wait<2>();
    uint32_t res[20];
    mbar_wait(BAR(res), 0);
    const uint32_t ta = (8 * (mi >> 1) + mj) * 128 + (((2 * w + (mi & 1)) ^ mj) << 4);
    if (layer == 0) {
        const int tok = 16 * w + 8 * (mi & 1) + mj;
#pragma unroll
        for (int k = 0; k < 4; k++)
            ldsm_x4(res[4 * k], res[4 * k + 1], res[4 * k + 2], res[4 * k + 3], sb + W_RES + wg * 10240 + tok * 128 + (((2 * k + (mi >> 1)) ^ mj) << 4));
        ldsm_x4(res[16], res[17], res[18], res[19], sb + W_RES + wg * 10240 + 8192 + tok * 32 + (((mi >> 1) ^ (mj >> 2)) << 4));
    } else {
#pragma unroll
        for (int k = 0; k < 5; k++) ldsm_x4_t(res[4 * k], res[4 * k + 1], res[4 * k + 2], res[4 * k + 3], sb + W_RES + wg * 10240 + k * 2048 + ta);
    }
    mbar_wait(BAR(qdone), 0);
    wg_wait<0>();
    TS(19);
#pragma unroll
    for (int i = 0; i < 20; i++) {
        const uint32_t y = pack2(aw[2 * i], aw[2 * i + 1]);
        asm("add.rn.bf16x2 %0, %0, %1;" : "+r"(res[i]) : "r"(y));
    }
    auto stage_out = [&] {
        const uint32_t mk = (g & 3) ? 0u : 0x00010001u;
#pragma unroll
        for (int k = 0; k < 5; k++) {
            uint32_t m[4];
#pragma unroll
            for (int i = 0; i < 4; i++) m[i] = (res[4 * k + i] & ~mk) | (mk & (0u - ob));
            stsm_x4_t(sb + W_OUT + wg * 10240 + k * 2048 + ta, m[0], m[1], m[2], m[3]);
        }
        fence_async_smem();
        __syncwarp();
        if (lane == 0) mbar_arrive(BAR(staged) + 8 * wg);
        TS(20);
    };
    if (!S_FIRST) stage_out();
    {
        float sm[4] = {0.f, 0.f, 0.f, 0.f}, d0[4] = {0.f, 0.f, 0.f, 0.f}, d1[4] = {0.f, 0.f, 0.f, 0.f};
#pragma unroll
        for (int k = 0; k < 5; k++) {
            mma16816(sm, res[4 * k], res[4 * k + 1], res[4 * k + 2], res[4 * k + 3], 0x3F803F80u, 0x3F803F80u);
            mma16816(d0, res[4 * k], res[4 * k + 1], res[4 * k + 2], res[4 * k + 3], res[4 * k], res[4 * k + 2]);
            mma16816(d1, res[4 * k], res[4 * k + 1], res[4 * k + 2], res[4 * k + 3], res[4 * k + 1], res[4 * k + 3]);
        }
        if (q == (g >> 1))
            st_ll4(&g_sp2[blk][warp][hg][g], (__float_as_uint(sm[0]) & ~1u) | ob, __float_as_uint((g & 1) ? d0[1] : d0[0]), __float_as_uint(sm[2]),
                   __float_as_uint((g & 1) ? d1[3] : d1[2]));
    }
    TS(23);
    if (S_FIRST) stage_out();
    if (layer) {
#pragma unroll
        for (int k = 0; k < 5; k++) stsm_x4_t(sb + W_RES + wg * 10240 + k * 2048 + ta, res[4 * k], res[4 * k + 1], res[4 * k + 2], res[4 * k + 3]);
    }
    if (O_TPOS == 9) conv_tables();
    TS(21);
    named_bar(1 + wg, 128);
    TS(22);
    TS_PHASE(2 * layer + 1);
    TS(0);
    indices();
    conv_wg<2>(5 * bx + 2 * (warp >> 2), layer, sb + F_EO + (warp >> 2) * 8192, sb + (warp >> 2) * Q_SB, sb + F_S23, s2u(&s_kg.kexp[2 * (warp >> 2)]),
               s2u(&s_epoch), sb + 3 * Q_SB, BAR(st), warp, lane, fa1, ftw, [] {}, [&] {
        if (warp == 0) {
            const bf16* pp = g_x1T + (size_t)(5 * bx + 4) * XP + 64 * lane + 60;
            mbar_wait(BAR(staged) + 8, 0);
            uint32_t v;
            int spin = 0;
            if (X_HINT) do { asm volatile("ld.relaxed.gpu.global.u32 %0, [%1];" : "=r"(v) : "l"(pp) : "memory"); } while (__any_sync(~0u, ~(v ^ layer) & 1u) && ++spin < (1 << 18));
            if (lane == 0) mbar_arrive(BAR(ardy));
        } else {
            mbar_wait(BAR(ardy), 0);
        }
    }, [] {} TS_PASS);
    conv_done();
    asm volatile("setmaxnreg.dec.sync.aligned.u32 168;");
    }
    named_bar(1 + (warp >> 2), 128);
    asm volatile("setmaxnreg.dec.sync.aligned.u32 %0;" ::"n"(504 - 2 * R_CONS));
    }
    indices();
    const int cq = 4 * (warp >> 1) + (lane & 3), tg = 8 * (warp & 1) + (lane >> 2);
    const uint32_t fb = ~EPOCH & 1u;
    uint2 xr[4][2];
    __syncthreads();
    if (tid < 320) {
#pragma unroll
        for (int i = 0; i < 8; i++) {
            const int ch = 4 * cq + (i >> 1);
            asm volatile("ld.shared.v2.u32 {%0, %1}, [%2];" : "=r"(xr[i >> 1][i & 1].x), "=r"(xr[i >> 1][i & 1].y)
                         : "r"(sb + W_RES + (i & 1) * 10240 + ch * 128 + (((tg >> 1) ^ (ch & 7)) << 4) + (tg & 1) * 8) : "memory");
        }
    }
    if (tid < 320) {
        const uint4* src = &g_of[hg][blk][64 * cq + tg];
        uint4 v[4];
#pragma unroll
        for (int i = 0; i < 4; i++) v[i] = make_uint4(~fb, 0, 0, 0);
        int spin = 0;
        while (true) {
#pragma unroll
            for (int i = 0; i < 4; i++) if ((v[i].x ^ fb) & 1u) v[i] = ld_ll4(src + 16 * i);
            if (!(((v[0].x ^ fb) | (v[1].x ^ fb) | (v[2].x ^ fb) | (v[3].x ^ fb)) & 1u) || ++spin >= (1 << 18)) break;
        }
        TS(21);
#pragma unroll
        for (int i = 0; i < 16; i++) asm("add.rn.bf16x2 %0, %0, %1;" : "+r"(u4r(v[i >> 2], i & 3)) : "r"((i & 1) ? xr[i >> 2][(i >> 1) & 1].y : xr[i >> 2][(i >> 1) & 1].x));
#pragma unroll
        for (int j = 0; j < 8; j++) {
            const uint32_t sel = (j & 2) ? 0x7632 : 0x5410;
            const int k = 2 * (j & 1) + (j >> 2);
            asm volatile("st.shared.v2.u32 [%0], {%1, %2};" ::"r"(sb + 2 * Q_SB + (16 * j + tg) * 160 + cq * 8),
                         "r"(__byte_perm(u4(v[0], k), u4(v[1], k), sel)), "r"(__byte_perm(u4(v[2], k), u4(v[3], k), sel)) : "memory");
        }
        fence_async_smem();
    }
    __syncthreads();
    if (warp == 0 && elect_one()) {
        asm volatile("cp.async.bulk.tensor.3d.global.shared::cta.bulk_group [%0, {%2, %3, 0}], [%1];" ::"l"(TMAP(9)), "r"(sb + 2 * Q_SB), "r"(80 * hg), "r"(16 * blk) : "memory");
        bulk_commit();
        asm volatile("cp.async.bulk.wait_group.read 0;" ::: "memory");
    }
    if (bx == 0 && tid == 0) g_epoch = EPOCH + 1;
    TS(22);
    TS_END;
}
typedef CUresult (*EncodeTiledFn)(CUtensorMap*, CUtensorMapDataType, cuuint32_t, void*, const cuuint64_t*, const cuuint64_t*, const cuuint32_t*,
                                  const cuuint32_t*, CUtensorMapInterleave, CUtensorMapSwizzle, CUtensorMapL2promotion, CUtensorMapFloatOOBfill);

static void make_map(EncodeTiledFn enc, CUtensorMap* m, const void* base, int rank, const cuuint64_t* dims, const cuuint64_t* strides,
                     const cuuint32_t* box, CUtensorMapSwizzle sw) {
    cuuint32_t es[4] = {1, 1, 1, 1};
    enc(m, CU_TENSOR_MAP_DATA_TYPE_BFLOAT16, rank, (void*)base, dims, strides, box, es, CU_TENSOR_MAP_INTERLEAVE_NONE, sw,
        sw == CU_TENSOR_MAP_SWIZZLE_128B ? CU_TENSOR_MAP_L2_PROMOTION_L2_128B : CU_TENSOR_MAP_L2_PROMOTION_NONE, CU_TENSOR_MAP_FLOAT_OOB_FILL_NONE);
}

template <typename... KArgs, typename... Args>
static void launch(void (*kern)(KArgs...), int grid, int block, int smem, int cluster, bool pdl, Args... args) {
    cudaLaunchConfig_t cfg = {};
    cfg.gridDim = dim3(grid); cfg.blockDim = dim3(block); cfg.dynamicSmemBytes = smem; cfg.stream = cudaStreamPerThread;
    cudaLaunchAttribute at[2];
    int n = 0;
    if (cluster > 1) { at[n].id = cudaLaunchAttributeClusterDimension; at[n].val.clusterDim.x = cluster; at[n].val.clusterDim.y = 1; at[n].val.clusterDim.z = 1; n++; }
    if (pdl) { at[n].id = cudaLaunchAttributeProgrammaticStreamSerialization; at[n].val.programmaticStreamSerializationAllowed = 1; n++; }
    cfg.attrs = at; cfg.numAttrs = n;
    cudaLaunchKernelEx(&cfg, kern, KArgs(args)...);
}

struct HostState {
    bool ready = false;
    const void* key[4] = {nullptr, nullptr, nullptr, nullptr};
    CUtensorMap mX[2], mRes[2], mW, mWr, mWo, mOut, mFin, mResA;
    bf16 *x1T, *x2T;
};

extern "C" void kernel_launch(void* const* d_in, const int* in_sizes, int n_in, void* d_out, int out_size) {
    const bf16* x = (const bf16*)d_in[0];
    const bf16* wqkv = (const bf16*)d_in[1];
    const bf16* wo = (const bf16*)d_in[2];
    const bf16* lar = (const bf16*)d_in[4];
    const bf16* aim = (const bf16*)d_in[5];
    const bf16* cre = (const bf16*)d_in[6];
    const bf16* cim = (const bf16*)d_in[7];
    const bf16* logdt = (const bf16*)d_in[8];
    const bf16* dskip = (const bf16*)d_in[9];
    static HostState hs;
    if (!hs.ready || hs.key[0] != wqkv || hs.key[1] != wo || hs.key[2] != x || hs.key[3] != d_out) {
        void* fn = nullptr;
        cudaDriverEntryPointQueryResult qr;
        cudaGetDriverEntryPoint("cuTensorMapEncodeTiled", &fn, cudaEnableDefault, &qr);
        EncodeTiledFn enc = (EncodeTiledFn)fn;
        cudaGetSymbolAddress((void**)&hs.x1T, g_x1T);
        cudaGetSymbolAddress((void**)&hs.x2T, g_x2T);
        {
            cuuint64_t d[3] = {DM, SEQ / 2, 2}, s[2] = {DM * 4, DM * 2};
            cuuint32_t b[3] = {64, 64, 2}, ba[3] = {64, 64, 1}, br[3] = {16, 64, 1};
            make_map(enc, &hs.mX[0], x, 3, d, s, b, CU_TENSOR_MAP_SWIZZLE_128B);
            make_map(enc, &hs.mResA, x, 3, d, s, ba, CU_TENSOR_MAP_SWIZZLE_128B);
            make_map(enc, &hs.mRes[0], x, 3, d, s, br, CU_TENSOR_MAP_SWIZZLE_32B);
            cuuint64_t d2[3] = {SEQ / 2, DM, 2}, s2[2] = {XP * 2, SEQ};
            cuuint32_t b2[3] = {64, 80, 2};
            make_map(enc, &hs.mX[1], hs.x2T, 3, d2, s2, b, CU_TENSOR_MAP_SWIZZLE_128B);
            make_map(enc, &hs.mRes[1], hs.x2T, 3, d2, s2, b2, CU_TENSOR_MAP_SWIZZLE_128B);
            cuuint64_t d3[2] = {SEQ, DM};
            make_map(enc, &hs.mOut, hs.x1T, 2, d3, s2, b2, CU_TENSOR_MAP_SWIZZLE_128B);
        }
        { cuuint64_t d[2] = {3 * DM, DM}, s[1] = {3 * DM * 2}; cuuint32_t b[2] = {64, 32};
          make_map(enc, &hs.mW, wqkv, 2, d, s, b, CU_TENSOR_MAP_SWIZZLE_128B); }
        { cuuint64_t d[3] = {DM, DM, 3}, s[2] = {3 * DM * 2, DM * 2}; cuuint32_t b[3] = {16, 32, 3};
          make_map(enc, &hs.mWr, wqkv, 3, d, s, b, CU_TENSOR_MAP_SWIZZLE_32B); }
        { cuuint64_t d[4] = {8, 8, DM / 8, DM / 8}, s[3] = {DM * 2, 16, DM * 16}; cuuint32_t b[4] = {8, 8, 10, 5};
          make_map(enc, &hs.mWo, wo, 4, d, s, b, CU_TENSOR_MAP_SWIZZLE_NONE); }
        { cuuint64_t d[3] = {DM, SEQ / 8, 8}, s[2] = {DM * 16, DM * 2}; cuuint32_t b[3] = {80, 16, 8};
          make_map(enc, &hs.mFin, d_out, 3, d, s, b, CU_TENSOR_MAP_SWIZZLE_NONE); }
        cudaFuncSetAttribute(fused_kernel, cudaFuncAttributeMaxDynamicSharedMemorySize, Q_SMEM);
        hs.key[0] = wqkv; hs.key[1] = wo; hs.key[2] = x; hs.key[3] = d_out;
        hs.ready = true;
    }
    const SsmParams sp = {lar, aim, cre, cim, logdt, dskip};
    launch(fused_kernel, 128, 384, Q_SMEM, 2, false, sp, hs.mX[0], hs.mX[1], hs.mW, hs.mWr, hs.mRes[0], hs.mRes[1], hs.mOut, hs.mWo, hs.mFin, hs.mResA);
}
```

```cpp
#include <cuda_runtime.h>
#include <cuda.h>
#include <cuda_bf16.h>
#include <cuda_fp16.h>
#include <stdint.h>

typedef __nv_bfloat16 bf16;

constexpr int SEQ = 2048;
constexpr int DM  = 640;
constexpr int XP  = SEQ + 64;
constexpr int NMODE = 192;

__device__ __forceinline__ uint32_t s2u(const void* p) { return (uint32_t)__cvta_generic_to_shared(p); }
__device__ __forceinline__ void mbar_init(uint32_t b, int c) { asm volatile("mbarrier.init.shared::cta.b64 [%0], %1;" ::"r"(b), "r"(c)); }
__device__ __forceinline__ void mbar_expect(uint32_t b, uint32_t bytes) { asm volatile("mbarrier.arrive.expect_tx.shared::cta.b64 _, [%0], %1;" ::"r"(b), "r"(bytes) : "memory"); }
__device__ __forceinline__ void mbar_arrive(uint32_t b) { asm volatile("mbarrier.arrive.shared::cta.b64 _, [%0];" ::"r"(b) : "memory"); }
__device__ __forceinline__ void mbar_arrive_cta(uint32_t b, uint32_t cta) {
    asm volatile("{\n.reg .b32 ra;\nmapa.shared::cluster.u32 ra, %0, %1;\nmbarrier.arrive.shared::cluster.b64 _, [ra];\n}" ::"r"(b), "r"(cta) : "memory");
}
__device__ __forceinline__ void mbar_wait(uint32_t b, uint32_t ph) {
#ifdef M_PLAIN
    asm volatile("{\n.reg .pred p;\nW: mbarrier.try_wait.parity.shared::cta.b64 p, [%0], %1;\n@!p bra W;\n}" ::"r"(b), "r"(ph) : "memory");
    return;
#endif
    asm volatile("{\n.reg .pred p;\n.reg .u32 n;\nmbarrier.try_wait.parity.shared::cta.b64 p, [%0], %1;\n@p bra D;\nmov.u32 n, 0;\n"
                 "W: mbarrier.try_wait.parity.shared::cta.b64 p, [%0], %1;\n@p bra D;\nadd.u32 n, n, 1;\nsetp.lt.u32 p, n, 4194304;\n@p bra W;\ntrap;\nD:\n}"
                 ::"r"(b), "r"(ph) : "memory");
}
__device__ __forceinline__ void fence_mbar_init() { asm volatile("fence.mbarrier_init.release.cluster;" ::: "memory"); }
__device__ __forceinline__ void cluster_sync() { asm volatile("barrier.cluster.arrive.aligned;\nbarrier.cluster.wait.aligned;" ::: "memory"); }
__device__ __forceinline__ void pdl_wait() { asm volatile("griddepcontrol.wait;" ::: "memory"); }
__device__ __forceinline__ void pdl_launch() { asm volatile("griddepcontrol.launch_dependents;" ::: "memory"); }
__device__ __forceinline__ void named_bar(int id, int n) { asm volatile("bar.sync %0, %1;" ::"r"(id), "r"(n) : "memory"); }
__device__ __forceinline__ void fence_async_smem() { asm volatile("fence.proxy.async.shared::cta;" ::: "memory"); }

__device__ __forceinline__ void tma2d(uint32_t dst, const CUtensorMap* m, int c0, int c1, uint32_t bar) {
    asm volatile("cp.async.bulk.tensor.2d.shared::cluster.global.mbarrier::complete_tx::bytes [%0], [%1, {%3, %4}], [%2];"
                 ::"r"(dst), "l"(m), "r"(bar), "r"(c0), "r"(c1) : "memory");
}
__device__ __forceinline__ void tma2d_mc(uint32_t dst, const CUtensorMap* m, int c0, int c1, uint32_t bar, uint16_t mask) {
    asm volatile("cp.async.bulk.tensor.2d.shared::cluster.global.mbarrier::complete_tx::bytes.multicast::cluster [%0], [%1, {%3, %4}], [%2], %5;"
                 ::"r"(dst), "l"(m), "r"(bar), "r"(c0), "r"(c1), "h"(mask) : "memory");
}
__device__ __forceinline__ void tma3d(uint32_t dst, const CUtensorMap* m, int c0, int c1, int c2, uint32_t bar) {
    asm volatile("cp.async.bulk.tensor.3d.shared::cluster.global.mbarrier::complete_tx::bytes [%0], [%1, {%3, %4, %5}], [%2];"
                 ::"r"(dst), "l"(m), "r"(bar), "r"(c0), "r"(c1), "r"(c2) : "memory");
}
__device__ __forceinline__ void tma3d_mc(uint32_t dst, const CUtensorMap* m, int c0, int c1, int c2, uint32_t bar, uint16_t mask) {
    asm volatile("cp.async.bulk.tensor.3d.shared::cluster.global.mbarrier::complete_tx::bytes.multicast::cluster [%0], [%1, {%3, %4, %5}], [%2], %6;"
                 ::"r"(dst), "l"(m), "r"(bar), "r"(c0), "r"(c1), "r"(c2), "h"(mask) : "memory");
}
__device__ __forceinline__ void bulk_g2s(uint32_t dst, const void* src, uint32_t bytes, uint32_t bar) {
    asm volatile("cp.async.bulk.shared::cluster.global.mbarrier::complete_tx::bytes [%0], [%1], %2, [%3];"
                 ::"r"(dst), "l"(src), "r"(bytes), "r"(bar) : "memory");
}
__device__ __forceinline__ void bulk_g2s_mc(uint32_t dst, const void* src, uint32_t bytes, uint32_t bar, uint16_t mask) {
    asm volatile("cp.async.bulk.shared::cluster.global.mbarrier::complete_tx::bytes.multicast::cluster [%0], [%1], %2, [%3], %4;"
                 ::"r"(dst), "l"(src), "r"(bytes), "r"(bar), "h"(mask) : "memory");
}
__device__ __forceinline__ void prefetch_l2(const void* p, uint32_t bytes) { asm volatile("cp.async.bulk.prefetch.L2.global [%0], %1;" ::"l"(p), "r"(bytes) : "memory"); }
__device__ __forceinline__ void prefetch_tmap(const CUtensorMap* m) { asm volatile("prefetch.tensormap [%0];" ::"l"(m) : "memory"); }

__device__ __forceinline__ void wg_fence() { asm volatile("wgmma.fence.sync.aligned;" ::: "memory"); }
__device__ __forceinline__ void wg_commit() { asm volatile("wgmma.commit_group.sync.aligned;" ::: "memory"); }
template <int N> __device__ __forceinline__ void wg_wait() { asm volatile("wgmma.wait_group.sync.aligned %0;" ::"n"(N) : "memory"); }
__device__ __forceinline__ uint64_t mkdesc(uint32_t addr, uint32_t lbo, uint32_t sbo, uint32_t mode) {
    return (uint64_t)((addr & 0x3FFFF) >> 4) | ((uint64_t)(lbo >> 4) << 16) | ((uint64_t)(sbo >> 4) << 32) | ((uint64_t)mode << 62);
}

__device__ __forceinline__ void mma16816(float (&c)[4], uint32_t a0, uint32_t a1, uint32_t a2, uint32_t a3, uint32_t b0, uint32_t b1) {
    asm("mma.sync.aligned.m16n8k16.row.col.f32.bf16.bf16.f32 {%0,%1,%2,%3},{%4,%5,%6,%7},{%8,%9},{%0,%1,%2,%3};"
                 : "+f"(c[0]), "+f"(c[1]), "+f"(c[2]), "+f"(c[3]) : "r"(a0), "r"(a1), "r"(a2), "r"(a3), "r"(b0), "r"(b1));
}
__device__ __forceinline__ void mma1688(float (&c)[4], uint32_t a0, uint32_t a1, uint32_t b0) {
    asm("mma.sync.aligned.m16n8k8.row.col.f32.bf16.bf16.f32 {%0,%1,%2,%3},{%4,%5},{%6},{%0,%1,%2,%3};"
                 : "+f"(c[0]), "+f"(c[1]), "+f"(c[2]), "+f"(c[3]) : "r"(a0), "r"(a1), "r"(b0));
}
__device__ __forceinline__ void ldsm_x4(uint32_t& r0, uint32_t& r1, uint32_t& r2, uint32_t& r3, uint32_t a) {
    asm volatile("ldmatrix.sync.aligned.m8n8.x4.shared.b16 {%0,%1,%2,%3}, [%4];" : "=r"(r0), "=r"(r1), "=r"(r2), "=r"(r3) : "r"(a) : "memory");
}
__device__ __forceinline__ void ldsm_x4_t(uint32_t& r0, uint32_t& r1, uint32_t& r2, uint32_t& r3, uint32_t a) {
    asm volatile("ldmatrix.sync.aligned.m8n8.x4.trans.shared.b16 {%0,%1,%2,%3}, [%4];" : "=r"(r0), "=r"(r1), "=r"(r2), "=r"(r3) : "r"(a) : "memory");
}
__device__ __forceinline__ void ldsm_x2(uint32_t& r0, uint32_t& r1, uint32_t a) {
    asm volatile("ldmatrix.sync.aligned.m8n8.x2.shared.b16 {%0,%1}, [%2];" : "=r"(r0), "=r"(r1) : "r"(a) : "memory");
}
__device__ __forceinline__ void ldsm_x2_t(uint32_t& r0, uint32_t& r1, uint32_t a) {
    asm volatile("ldmatrix.sync.aligned.m8n8.x2.trans.shared.b16 {%0,%1}, [%2];" : "=r"(r0), "=r"(r1) : "r"(a) : "memory");
}
__device__ __forceinline__ void stsm_x4(uint32_t a, uint32_t r0, uint32_t r1, uint32_t r2, uint32_t r3) {
    asm volatile("stmatrix.sync.aligned.m8n8.x4.shared.b16 [%0], {%1,%2,%3,%4};" ::"r"(a), "r"(r0), "r"(r1), "r"(r2), "r"(r3) : "memory");
}
__device__ __forceinline__ void stsm_x4_t(uint32_t a, uint32_t r0, uint32_t r1, uint32_t r2, uint32_t r3) {
    asm volatile("stmatrix.sync.aligned.m8n8.x4.trans.shared.b16 [%0], {%1,%2,%3,%4};" ::"r"(a), "r"(r0), "r"(r1), "r"(r2), "r"(r3) : "memory");
}
__device__ __forceinline__ void stsm_x2(uint32_t a, uint32_t r0, uint32_t r1) {
    asm volatile("stmatrix.sync.aligned.m8n8.x2.shared.b16 [%0], {%1,%2};" ::"r"(a), "r"(r0), "r"(r1) : "memory");
}
__device__ __forceinline__ uint32_t movm_t(uint32_t a) {
    uint32_t d;
    asm volatile("movmatrix.sync.aligned.m8n8.trans.b16 %0, %1;" : "=r"(d) : "r"(a));
    return d;
}
__device__ __forceinline__ uint32_t lds32(uint32_t a) { uint32_t v; asm volatile("ld.shared.u32 %0, [%1];" : "=r"(v) : "r"(a) : "memory"); return v; }
__device__ __forceinline__ uint32_t ldsv32(uint32_t a) { uint32_t v; asm volatile("ld.volatile.shared.u32 %0, [%1];" : "=r"(v) : "r"(a) : "memory"); return v; }
__device__ __forceinline__ void sts32(uint32_t a, uint32_t v) { asm volatile("st.shared.u32 [%0], %1;" ::"r"(a), "r"(v) : "memory"); }
__device__ __forceinline__ uint4 lds128(uint32_t a) { uint4 v; asm volatile("ld.shared.v4.u32 {%0,%1,%2,%3}, [%4];" : "=r"(v.x), "=r"(v.y), "=r"(v.z), "=r"(v.w) : "r"(a) : "memory"); return v; }
__device__ __forceinline__ void sts128(uint32_t a, uint4 v) { asm volatile("st.shared.v4.u32 [%0], {%1,%2,%3,%4};" ::"r"(a), "r"(v.x), "r"(v.y), "r"(v.z), "r"(v.w) : "memory"); }

__device__ __forceinline__ void stg128(void* p, uint4 v) { asm volatile("st.global.v4.u32 [%0], {%1,%2,%3,%4};" ::"l"(p), "r"(v.x), "r"(v.y), "r"(v.z), "r"(v.w) : "memory"); }

__device__ __forceinline__ uint4 ldg128(const void* p) { uint4 v; asm volatile("ld.global.v4.u32 {%0,%1,%2,%3}, [%4];" : "=r"(v.x), "=r"(v.y), "=r"(v.z), "=r"(v.w) : "l"(p) : "memory"); return v; }
__device__ __forceinline__ uint2 ldg64(const void* p) { uint2 v; asm volatile("ld.global.v2.u32 {%0,%1}, [%2];" : "=r"(v.x), "=r"(v.y) : "l"(p) : "memory"); return v; }
__device__ __forceinline__ uint32_t ldg32(const void* p) { uint32_t v; asm volatile("ld.global.u32 %0, [%1];" : "=r"(v) : "l"(p) : "memory"); return v; }

__device__ __forceinline__ uint32_t pack2(float lo, float hi) {
    uint32_t r;
    asm("cvt.rn.bf16x2.f32 %0, %1, %2;" : "=r"(r) : "f"(hi), "f"(lo));
    return r;
}
__device__ __forceinline__ float bf_lo(uint32_t v) { return __uint_as_float(v << 16); }
__device__ __forceinline__ float bf_hi(uint32_t v) { return __uint_as_float(v & 0xFFFF0000u); }
__device__ __forceinline__ float rbf(float x) { return __uint_as_float(pack2(0.f, x) & 0xFFFF0000u); }
__device__ __forceinline__ float ex2(float x) { float r; asm("ex2.approx.ftz.f32 %0, %1;" : "=f"(r) : "f"(x)); return r; }

__device__ __forceinline__ float2 ln_finish(float sum, float sumsq) {
    const float m = sum * (1.0f / DM);
    const float v = fmaxf(fmaf(sumsq, 1.0f / DM, -m * m), 0.f);
    float s, r;
    asm("sqrt.approx.ftz.f32 %0, %1;" : "=f"(s) : "f"(rbf(rbf(v) + 1e-5f)));
    asm("rcp.approx.ftz.f32 %0, %1;" : "=f"(r) : "f"(rbf(s)));
    return make_float2(m, r);
}
__device__ __forceinline__ uint32_t ln_finish_packed(float sum, float sumsq) {
    const float m = sum * (1.0f / DM);
    const float v = fmaxf(fmaf(sumsq, 1.0f / DM, -m * m), 0.f);
    float s;
    asm("sqrt.approx.ftz.f32 %0, %1;" : "=f"(s) : "f"(rbf(rbf(v) + 1e-5f)));
    return pack2(s, m);
}
__device__ __forceinline__ float frsq(float x) { float r; asm("rsqrt.approx.ftz.f32 %0, %1;" : "=f"(r) : "f"(x)); return r; }
__device__ __forceinline__ float frcp(float x) { float r; asm("rcp.approx.ftz.f32 %0, %1;" : "=f"(r) : "f"(x)); return r; }
__device__ __forceinline__ bool elect_one() {
    uint32_t p;
    asm volatile("{\n.reg .pred p;\nelect.sync _|p, 0xffffffff;\nselp.u32 %0, 1, 0, p;\n}" : "=r"(p));
    return p != 0;
}
__device__ __forceinline__ void cluster_arrive_relaxed() { asm volatile("barrier.cluster.arrive.relaxed.aligned;" ::: "memory"); }
__device__ __forceinline__ void cluster_wait() { asm volatile("barrier.cluster.wait.aligned;" ::: "memory"); }
__device__ __forceinline__ unsigned long long ld_ll(const unsigned long long* p) {
    unsigned long long v;
    asm volatile("ld.relaxed.gpu.global.b64 %0, [%1];" : "=l"(v) : "l"(p) : "memory");
    return v;
}
__device__ __forceinline__ void st_ll(unsigned long long* p, uint32_t payload, uint32_t tag) {
    const unsigned long long v = (unsigned long long)payload | ((unsigned long long)tag << 32);
    asm volatile("st.relaxed.gpu.global.b64 [%0], %1;" ::"l"(p), "l"(v) : "memory");
}
__device__ __forceinline__ uint4 ld_ll4(const uint4* p) {
    uint4 v;
    asm volatile("{\n.reg .b128 t;\n.reg .b64 a, b;\nld.relaxed.gpu.global.b128 t, [%4];\nmov.b128 {a, b}, t;\nmov.b64 {%0, %1}, a;\nmov.b64 {%2, %3}, b;\n}"
                 : "=r"(v.x), "=r"(v.y), "=r"(v.z), "=r"(v.w) : "l"(p) : "memory");
    return v;
}
__device__ __forceinline__ void st_ll4(uint4* p, uint32_t x, uint32_t y, uint32_t z, uint32_t w) {
    asm volatile("{\n.reg .b128 t;\n.reg .b64 a, b;\nmov.b64 a, {%1, %2};\nmov.b64 b, {%3, %4};\nmov.b128 t, {a, b};\nst.relaxed.gpu.global.b128 [%0], t;\n}"
                 ::"l"(p), "r"(x), "r"(y), "r"(z), "r"(w) : "memory");
}

__device__ __forceinline__ void bulk_s2g(void* dst, uint32_t src, uint32_t bytes) {
    asm volatile("cp.async.bulk.global.shared::cta.bulk_group [%0], [%1], %2;" ::"l"(dst), "r"(src), "r"(bytes) : "memory");
}
__device__ __forceinline__ void bulk_commit() { asm volatile("cp.async.bulk.commit_group;" ::: "memory"); }
__device__ __forceinline__ void bulk_wait() { asm volatile("cp.async.bulk.wait_group 0;" ::: "memory"); }
__device__ __forceinline__ void fence_async_global() { asm volatile("fence.proxy.async.global;" ::: "memory"); }
__device__ __forceinline__ void fence_release() { asm volatile("fence.release.gpu;" ::: "memory"); }
__device__ __forceinline__ void fence_acquire() { asm volatile("fence.acquire.gpu;" ::: "memory"); }
template<int TA, int TB>
__device__ __forceinline__ void wgmma_n192(float (&d)[96], uint64_t da, uint64_t db, int scale_d) {
  asm volatile("{\n.reg .pred p;\nsetp.ne.b32 p, %98, 0;\n"
    "wgmma.mma_async.sync.aligned.m64n192k16.f32.bf16.bf16 "
    "{%0, %1, %2, %3, %4, %5, %6, %7, %8, %9, %10, %11, %12, %13, %14, %15, %16, %17, %18, %19, %20, %21, %22, %23, %24, %25, %26, %27, %28, %29, %30, %31, %32, %33, %34, %35, %36, %37, %38, %39, %40, %41, %42, %43, %44, %45, %46, %47, %48, %49, %50, %51, %52, %53, %54, %55, %56, %57, %58, %59, %60, %61, %62, %63, %64, %65, %66, %67, %68, %69, %70, %71, %72, %73, %74, %75, %76, %77, %78, %79, %80, %81, %82, %83, %84, %85, %86, %87, %88, %89, %90, %91, %92, %93, %94, %95}, %96, %97, p, 1, 1, %99, %100;\n}\n"
    : "+f"(d[0]), "+f"(d[1]), "+f"(d[2]), "+f"(d[3]), "+f"(d[4]), "+f"(d[5]), "+f"(d[6]), "+f"(d[7]), "+f"(d[8]), "+f"(d[9]), "+f"(d[10]), "+f"(d[11]), "+f"(d[12]), "+f"(d[13]), "+f"(d[14]), "+f"(d[15]), "+f"(d[16]), "+f"(d[17]), "+f"(d[18]), "+f"(d[19]), "+f"(d[20]), "+f"(d[21]), "+f"(d[22]), "+f"(d[23]), "+f"(d[24]), "+f"(d[25]), "+f"(d[26]), "+f"(d[27]), "+f"(d[28]), "+f"(d[29]), "+f"(d[30]), "+f"(d[31]), "+f"(d[32]), "+f"(d[33]), "+f"(d[34]), "+f"(d[35]), "+f"(d[36]), "+f"(d[37]), "+f"(d[38]), "+f"(d[39]), "+f"(d[40]), "+f"(d[41]), "+f"(d[42]), "+f"(d[43]), "+f"(d[44]), "+f"(d[45]), "+f"(d[46]), "+f"(d[47]), "+f"(d[48]), "+f"(d[49]), "+f"(d[50]), "+f"(d[51]), "+f"(d[52]), "+f"(d[53]), "+f"(d[54]), "+f"(d[55]), "+f"(d[56]), "+f"(d[57]), "+f"(d[58]), "+f"(d[59]), "+f"(d[60]), "+f"(d[61]), "+f"(d[62]), "+f"(d[63]), "+f"(d[64]), "+f"(d[65]), "+f"(d[66]), "+f"(d[67]), "+f"(d[68]), "+f"(d[69]), "+f"(d[70]), "+f"(d[71]), "+f"(d[72]), "+f"(d[73]), "+f"(d[74]), "+f"(d[75]), "+f"(d[76]), "+f"(d[77]), "+f"(d[78]), "+f"(d[79]), "+f"(d[80]), "+f"(d[81]), "+f"(d[82]), "+f"(d[83]), "+f"(d[84]), "+f"(d[85]), "+f"(d[86]), "+f"(d[87]), "+f"(d[88]), "+f"(d[89]), "+f"(d[90]), "+f"(d[91]), "+f"(d[92]), "+f"(d[93]), "+f"(d[94]), "+f"(d[95])
    : "l"(da), "l"(db), "r"(scale_d), "n"(TA), "n"(TB));
}

template<int TA, int TB>
__device__ __forceinline__ void wgmma_n48(float (&d)[24], uint64_t da, uint64_t db, int scale_d) {
  asm volatile("{\n.reg .pred p;\nsetp.ne.b32 p, %26, 0;\n"
    "wgmma.mma_async.sync.aligned.m64n48k16.f32.bf16.bf16 "
    "{%0, %1, %2, %3, %4, %5, %6, %7, %8, %9, %10, %11, %12, %13, %14, %15, %16, %17, %18, %19, %20, %21, %22, %23}, %24, %25, p, 1, 1, %27, %28;\n}\n"
    : "+f"(d[0]), "+f"(d[1]), "+f"(d[2]), "+f"(d[3]), "+f"(d[4]), "+f"(d[5]), "+f"(d[6]), "+f"(d[7]), "+f"(d[8]), "+f"(d[9]), "+f"(d[10]), "+f"(d[11]), "+f"(d[12]), "+f"(d[13]), "+f"(d[14]), "+f"(d[15]), "+f"(d[16]), "+f"(d[17]), "+f"(d[18]), "+f"(d[19]), "+f"(d[20]), "+f"(d[21]), "+f"(d[22]), "+f"(d[23])
    : "l"(da), "l"(db), "r"(scale_d), "n"(TA), "n"(TB));
}

__device__ __forceinline__ void wgmma_rs80(float (&d)[40], const uint4& a, uint64_t db, int scale_d) {
  asm volatile("{\n.reg .pred p;\nsetp.ne.b32 p, %45, 0;\n"
    "wgmma.mma_async.sync.aligned.m64n80k16.f32.bf16.bf16 {%0,%1,%2,%3,%4,%5,%6,%7,%8,%9,%10,%11,%12,%13,%14,%15,%16,%17,%18,%19,%20,%21,%22,%23,%24,%25,%26,%27,%28,%29,%30,%31,%32,%33,%34,%35,%36,%37,%38,%39}, {%40,%41,%42,%43}, %44, p, 1, 1, 1;\n}\n"
    : "+f"(d[0]), "+f"(d[1]), "+f"(d[2]), "+f"(d[3]), "+f"(d[4]), "+f"(d[5]), "+f"(d[6]), "+f"(d[7]), "+f"(d[8]), "+f"(d[9]), "+f"(d[10]), "+f"(d[11]), "+f"(d[12]), "+f"(d[13]), "+f"(d[14]), "+f"(d[15]), "+f"(d[16]), "+f"(d[17]), "+f"(d[18]), "+f"(d[19]), "+f"(d[20]), "+f"(d[21]), "+f"(d[22]), "+f"(d[23]), "+f"(d[24]), "+f"(d[25]), "+f"(d[26]), "+f"(d[27]), "+f"(d[28]), "+f"(d[29]), "+f"(d[30]), "+f"(d[31]), "+f"(d[32]), "+f"(d[33]), "+f"(d[34]), "+f"(d[35]), "+f"(d[36]), "+f"(d[37]), "+f"(d[38]), "+f"(d[39])
    : "r"(a.x), "r"(a.y), "r"(a.z), "r"(a.w), "l"(db), "r"(scale_d));
}

__device__ const __align__(1024) uint32_t c_fft[11264] = {
0x2ddc2dba,0x2fe62eb5,0x2ed02eb5,0xafffaf6e,0x2e1f2dfe,0x2e3f2fbc,0x2f022ee9,0xad27af30,0x2e5e2e3f,0x1fd92b5e,0x2f302f1a,0x244ea875,0x2e992e7c,0xad96a993,0x2f5a2f46,0x2e992c32,
0xad00ad72,0xa17eac32,0xa17ea515,0xabb79cb6,0xac07ac87,0x2dfe29f1,0x1fd99648,0xafedae99,0xa9f1ab05,0x2fd42fbc,0x26a1244e,0xad96af91,0xa765a8d5,0x2aaa2e3f,0x29932875,0x2515a8d5,
0xae99adfe,0xb000aee9,0xaf6eafbc,0x2c872f30,0xaf80af1a,0xac32af02,0xae7caf02,0xaaaa217e,0xaff4afc9,0x2b5e9cb6,0xad27addc,0xaff4ae7c,0xafedb000,0x2ffc2eb5,0xab05ac5d,0xacd8af5a,
0x2c072d27,0x9fd92bb7,0xadfead00,0x2fed2e1f,0x25db2993,0xaf6eacb0,0xaf6eaed0,0x2c5d2f46,0xa5151648,0xaddcafdd,0xafffafd4,0xac321648,0xabb7a934,0x28d5a814,0xafa0afed,0xaff4af30,
0x2f302e3f,0x2fed2f1a,0x28142b5e,0x2934a875,0x30002fc9,0x26a12ddc,0xa5db1cb6,0x30002e7c,0x2f462fd4,0xaed0aa4e,0xacb0aa4e,0x29932e99,0x2d272e5e,0xae3faffc,0xaf02adfe,0xae1fa814,
0xa9f1acd8,0x26a1ab05,0x2fd42ffc,0xad96afed,0x2515a30e,0x2fff2e1f,0x2ddc2f1a,0x2c32a30e,0x2d272aaa,0x28752e7c,0x28752c32,0x2fa02f80,0x2f912e99,0xaee9a9f1,0xa8141648,0x9fd92c87,
0xafa0ae7c,0xafafaf46,0x2d002993,0xafa0ac32,0xaf91b000,0x244eac5d,0x2fbc2eb5,0xab05af5a,0xac87ae5e,0x30002dfe,0x2f6e2ffc,0x2e992814,0x1cb6a875,0x25152e1f,0x2c322e1f,0x2d722ff4,
0x27652c87,0xa9932a4e,0xaaaaadba,0xa5152c87,0xabb7a44e,0xafa0af30,0x28d59fd9,0xaff4ae5e,0xaf91ae1f,0x2814abb7,0x2ee92d00,0x1fd9ad27,0xaf5aafff,0x2fd42ed0,0x2fd42fe6,0x30002ddc,
0x2f462f6e,0x2c322fdd,0x2e7c2fdd,0xa993b000,0xab5e2934,0xafafacd8,0xad00244e,0x2f1a2dfe,0xaee9afaf,0x2f30a17e,0xadfeaff8,0xafbca30e,0x2c5da765,0xa9f12ddc,0x2d969cb6,0x2c5dacb0,
0x2bb7a993,0x2f1aa515,0x2f1a2765,0xaff4aaaa,0x2e5e2fd4,0xab052dba,0x29342f6e,0x2ee9a6a1,0xadba1fd9,0xa5dbafed,0xafddac07,0xaa4e2dfe,0xacb0aff8,0x2ddc2f02,0x9cb6ae3f,0xa765aff8,
0xaeb5af91,0xaa4eafed,0x9648ae5e,0xac5d2d4d,0x2ddca17e,0x2e7c2e3f,0x2fc92e3f,0x1cb6afa0,0x2bb72fe6,0xaff8a993,0xab5e2aaa,0x2bb72fc9,0xafbcaa4e,0x2f30a5db,0xadfeafdd,0xaee9adba,
0xacd828d5,0xaf91230e,0xaf30af02,0x2c072fa0,0xac5dafff,0x2dbaac32,0x2dbaa515,0xae99addc,0x2fc929f1,0xa9932eb5,0x2aaa2fdd,0x2fe629f1,0xa30e2dfe,0xa17eafed,0xaff8ac07,0xafaf1fd9,
0x2dfe2faf,0x28142ff8,0xae5e217e,0x2ffc230e,0xaf5aa515,0xac87af46,0xa6a1af80,0xaf5a2765,0x1cb6ae99,0x2e7c2dba,0x2fc92dba,0x2ddcac5d,0x2f1a2ee9,0xafafab05,0xad002934,0xab5e2e5e,
0x2dbaa814,0x2fdd9fd9,0x25db2f91,0x2a4eaee9,0x27652faf,0xaf4628d5,0xaf80ae1f,0xa5152faf,0xafa0addc,0x2e3fac32,0x2e3fa515,0xa17eafff,0x2dfea6a1,0xacd82dba,0x244e2f6e,0x29342fd4,
0xad27afc9,0xa30eafff,0x2faf2d72,0xad27ae7c,0x2ffc2a4e,0x28142fdd,0xae5e25db,0x2dfe2dba,0xac5d2c07,0xaa4eaf91,0x9648af30,0xaeb5acd8,0xa993aff4,0x2c322f1a,0x2e7c2f1a,0x2f462bb7,
0xae7c26a1,0xafff1648,0x2d72aa4e,0xafc926a1,0x230eaee9,0x2ff89fd9,0x217e2f91,0x2fafa814,0x2d4d2fa0,0xafed230e,0xae5eaf02,0xaf9128d5,0xb000aaaa,0x2fdda515,0x2fdd2765,0x2f6ea993,
0x9cb63000,0xacb02fd4,0xa7652fd4,0x2ddcaf5a,0x217eaffc,0x2ff4ac07,0x2875afbc,0xaff82934,0xa44e2ff4,0xadfea8d5,0xa9342fa0,0x2cd82bb7,0x25dbafe6,0x16482f46,0x29f1af80,0x25dbafc9,
0x2ff41cb6,0x2e1f2765,0x2e1f2cb0,0xa875addc,0xafbca5db,0x1fd9af5a,0xad4dad96,0xacd82fdd,0x2f5a2934,0xaeb52ee9,0x2c5d2e5e,0x3000ab05,0xaed0ab5e,0x2f80a30e,0xaaaaaf02,0xacb0ab5e,
0x25dbaffc,0x2d96afbc,0x2f5aac07,0xafdd2934,0xaaaa2fa0,0xafc92875,0xafe62875,0x29932d27,0x2d00aed0,0x28d52d72,0x2ff89cb6,0x2d00afe6,0xae5e2d96,0x2d4dafd4,0xaf91a6a1,0xafed29f1,
0xafbca17e,0xad4da875,0x1fd9aff4,0xacd82ff8,0x2e992aaa,0xaa4e2fe6,0xaa4e2fc9,0x2fd4a993,0xacb0ad96,0x2fffac87,0x2d72aeb5,0xa765ad96,0x28752f30,0xab5eac07,0xaf1a2cd8,0xae3f2f91,
0xa9342ff4,0xae5e2fa0,0xaee9a8d5,0x2b052bb7,0x2d96aed0,0x2eb59cb6,0x2c872d72,0x2d96afe6,0xaf802c5d,0x2765af6e,0xa515af6e,0xaf4625db,0x2ff8a44e,0xaff42d4d,0xa8752ffc,0xa17e2ee9,
0x2f5a244e,0x2c5d2934,0xaeb52dfe,0x3000acd8,0xacb0ad00,0x2d72aff8,0x2fffa8d5,0xa765ad00,0x217e2f80,0xaf022515,0xaf02a765,0xaf1a2f46,0x2b05afdd,0xa8142f5a,0x2c072d96,0x2d4d25db,
0x2b5eafe6,0x2f02af80,0x230e2f46,0x2b5eafc9,0xaf302d96,0xacd8a6a1,0x2c07afd4,0xaf9129f1,0x2fdda44e,0xad962ffc,0xaf5a2d4d,0xa5db2ee9,0xad72abb7,0x2e7ca17e,0x2fc9a17e,0x2fffad00,
0xaed0a5db,0xaaaaa9f1,0x2f809648,0xacb0a5db,0x28752e5e,0xaf1a2f91,0xab5ead4d,0xae3f2fed,0x2b05aff8,0x2c072875,0xa8142ff4,0x2d4d217e,0xaf6e2d72,0x2eb5afc9,0x2eb5ae7c,0x2dbaafff,
0xaf802f5a,0xafc92e99,0xafe62e99,0x2f46ad96,0x28d52b05,0xaf022fed,0x230e2cd8,0x2fa0affc,0x2fbcaf02,0xa9342d27,0x2ffcae1f,0x2c07ae3f,0xa6a1ac32,0x2a4e9cb6,0x9648ad72,0xa6a1a515,
0x28752aaa,0xa8d52cb0,0xa8d52ed0,0x2e3faf80,0x2fedaeb5,0x29349648,0x2f30aa4e,0x2814ac5d,0x1648ad4d,0x2e99acd8,0x2c87afbc,0xa9f11fd9,0xafe62d27,0x2fffafaf,0xaddc230e,0xaed02d27,
0x2fd4af30,0x2f6eae5e,0x2dbaa44e,0xa6a19fd9,0x1cb6ad27,0x2fe6aff4,0x2ed0aff4,0xad722b5e,0xafaf2cb0,0x2e1faf46,0xa8d5a993,0xafaf2ed0,0xac072f6e,0x2934ac87,0xaffc2e99,0xafbc3000,
0xa44eab5e,0x2b05ad00,0x2f91afaf,0xafbc2f1a,0xafd42d72,0x1648a765,0x1648acb0,0xafdd2fff,0xac322f5a,0xaaaa26a1,0xaf802c87,0xae7c2f5a,0x2d009fd9,0xae1f2cd8,0xad272fbc,0xabb72d4d,
0xaffc2f02,0xaee92e1f,0x244ead27,0xad4d2e3f,0xa9f12e7c,0xafdd2f80,0xaeb52aaa,0xa9f12c32,0x2d72a5db,0xafe63000,0xaed03000,0x9cb626a1,0x2fa0afbc,0xaf022f91,0x230e2b05,0x28d5a44e,
0x96482c07,0xac872d4d,0xae992b05,0x29f1a814,0x2ed0abb7,0xa9932b5e,0xaf462ff8,0x2cb0abb7,0x2f1aafff,0xa30e2765,0xa30e2cb0,0x2e1fad72,0x1fd9ac5d,0x244e9648,0x2e5eaa4e,0x2f30aeb5,
0x2ff8aed0,0x2e3faddc,0xaf022fff,0x2ff8afe6,0x2d4daf6e,0x2ee9ae99,0xa44e2c87,0x2ffcb000,0xa6a1a814,0x2f6eaf30,0x2dbaa934,0x2fd4afed,0xaf462d00,0x2fc9afa0,0x2fe6afa0,0x2f80afaf,
0x2515ac5d,0x2d72ad96,0x1cb629f1,0x2c32ac5d,0xad002814,0x2d27ad4d,0x2e1fab05,0x2bb7ac07,0xaffc2f1a,0x2cd8ad00,0x2fedafaf,0x2b05ab5e,0xadba2f80,0x2c87acb0,0x2c87aed0,0x2a4eaaaa,
0x2f802f6e,0x2fc92fdd,0x2fe62fdd,0xaf46b000,0x2fa02f91,0x2bb72e5e,0x2ff42fed,0xa8d5ad4d,0x2fbc2faf,0xa934217e,0x2ffc2ff8,0x2c07230e,0x2fd42fc9,0xaf5aad72,0x30002fff,0x2fd42e7c,
0x2bb72aaa,0x2f1a2cb0,0x2f1a2ed0,0xaff4af80,0x2cd82c5d,0x2f303000,0x2f912f5a,0xac07aeb5,0x2dba2d4d,0x25db2cd8,0x2fdd2fbc,0x2a4e9fd9,0x2e7c2e1f,0xad72a875,0x2fff2ff4,0x2fc92e1f,
0xa6a1a934,0x29f1a44e,0x2d962cd8,0xafd4adfe,0x1cb6a17e,0x2fe62e3f,0x2ed02e3f,0xad72afa0,0x28752515,0x2d272f80,0x2fa02f46,0x2875a765,0x2c072a4e,0xa93425db,0x2ffc2fdd,0x2fbc2dba,
0xae5eaf1a,0xa934ae3f,0x2b052875,0xaee9ab5e,0xac5dad72,0x2dba2765,0x2dba2cb0,0xae99afff,0xa765aa4e,0x2f802fd4,0x2f462e99,0x2515aa4e,0x230e9fd9,0x217e2cd8,0x2ff82fbc,0x2faf2d4d,
0xaffcafaf,0xaee9aff8,0x244ea17e,0xad4da30e,0xaf6eafe6,0x25dbaaaa,0x2c5d2993,0xaf6eafc9,0xad72ae99,0x2fe62dba,0x2ed02dba,0x1cb6ac5d,0xa8d5ac07,0x2bb72f30,0x2ff42f91,0x2fa02cd8,
0xadbaac07,0xafddad4d,0xa5dbab05,0xaa4e2814,0xafc9af02,0xaaaaaf1a,0x2993217e,0xafe6af02,0xafa0afff,0x2e3f2765,0x2e3f2cb0,0xa17ead72,0xad4daeb5,0x2e5e3000,0x2fed2f5a,0x2f912c5d,
0xa17e2765,0xad001cb6,0xabb7addc,0xa17e2cb0,0xad4daa4e,0xaee9afdd,0x244ea5db,0xaffcadba,0xafd4aee9,0x29f1a934,0x2d962b05,0xa6a1ae5e,0xaf46aff4,0x2fc92f1a,0x2fe62f1a,0x2f802bb7,
0x2cb02eb5,0x1cb62dba,0xaddcaf6e,0x27652eb5,0xa30e2814,0xaff8ad4d,0xa17eab05,0xafafac07,0xadfeab5e,0xa44eae3f,0x2cd82875,0xa934af1a,0xb000af80,0x2fdd2cb0,0x2fdd2ed0,0x2f6e2aaa,
0x2d723000,0x25152fd4,0x2c322fd4,0x1cb6af5a,0xae1f9fd9,0xae3faee9,0xaf02a814,0x2d272f91,0xacd8aff4,0x2ffc28d5,0xab05afa0,0xafedabb7,0x2e992515,0xad962aaa,0x2f5a2993,0x2e99a765,
0x2ff42ddc,0x2e1f2ed0,0x2e1f2fe6,0xa875afff,0xa8142c87,0xaffca9f1,0xadfe1648,0x2e5e2e99,0xaf5aaf30,0x2eb5a814,0xac5dafed,0xb000a934,0x2c32a8d5,0xa9932e3f,0x2f462875,0x2e7ca8d5,
0x2e991fd9,0x30002814,0x2f6e2ee9,0xac87af91,0x29932fa0,0xaed02875,0xacb02875,0x2f462d27,0xaff4ac32,0x2b5eaddc,0xad27afff,0xaff4a515,0x244ead96,0x1fd92fd4,0x2f3026a1,0x2e5ea9f1,
0x2814ad27,0x2dfeabb7,0x2ffc2d00,0xae5eae1f,0x2e992f80,0xaa4e2e7c,0xaa4e2c32,0x2fd42aaa,0xae7c1648,0x9cb6afdd,0xaddcafd4,0xafc91648,0xa875af91,0x2b5e2fbc,0x2f1a244e,0x2e3fab05,
0xab05aff4,0x244eafa0,0x2fbc28d5,0xaf91abb7,0x30002c32,0x26a12fff,0xa5db2ddc,0x30002515,0xaaaa2c5d,0xac32af6e,0xae7caf6e,0xaf8025db,0xad27afed,0x2e3f2dfe,0x2f021fd9,0x2e1fac07,
0xaf5aae5e,0xac5daf30,0x2eb59fd9,0xb000a44e,0x2e7ca30e,0x2ddc2e1f,0x1cb62f1a,0x2fc9a30e,0x217e2f46,0xaf02acb0,0xaf02aed0,0xaf1a2993,0xaf30ae99,0x2fbc29f1,0x2ee99648,0x2dfeac87,
0xafa0a515,0xafafa993,0x2d00aaaa,0xafa02765,0x2934ad96,0x2fed26a1,0x28142fd4,0x2f30a9f1,0x2c872fed,0xb0009fd9,0xaf6eadfe,0xae992c07,0xafffabb7,0x2fe6a17e,0x2ed0a17e,0x2ddcad00,
0xac322c87,0xaf462a4e,0x2993adba,0xae7c2c87,0xa875afed,0x2f1aab05,0x2b5e2ffc,0x2e3facd8,0x2f302e1f,0xaee92bb7,0xafbcad00,0xadfe2d27,0xaf6e9cb6,0x2eb5ac32,0x2eb5a515,0x2dbaad72,
0xaaaa2f5a,0xaed02e99,0xacb02e99,0x2f80ad96,0x2b5eaf30,0x2fafa44e,0x2d00ae5e,0xaf1a9fd9,0xac072f02,0xab05ad27,0xad4d2e1f,0x28142e3f,0x2c5daed0,0xa9f12fff,0x2d96addc,0x2c5dafe6,
0x28752f80,0xa8d52fe6,0xa8d52fc9,0x2e3faf46,0xa44eafd4,0x2f91adba,0x2b05af6e,0xafbc26a1,0x96482ffc,0xae99a44e,0xac872ee9,0x29f12d4d,0x2515aff8,0x1cb62f02,0x2d72ae3f,0x2c32aff8,
0x2eb52b05,0x2a4e2cd8,0x16482fed,0x2c5daffc,0xad72ad27,0x2cb0aff4,0x2765aff4,0xafff2b5e,0x2bb72e7c,0xaff82aaa,0xab5e2f80,0x2bb72c32,0xa814af6e,0x2b052c87,0x2d4dae99,0x2c07b000,
0x2feda8d5,0x2f30a30e,0x29342f02,0x2814afa0,0xafd49cb6,0x1648aed0,0x1648afe6,0xafdd2d72,0x2ed029f1,0xaf462eb5,0xa9932fdd,0x2cb029f1,0xad00ad4d,0x2e1f244e,0x2d27aee9,0x2bb7affc,
0x2d4daf02,0x2fbcae1f,0x2cd82d27,0x9fd9ae3f,0xaf5a2cb0,0xac87a993,0xa6a1af46,0xaf5a2ed0,0x2fffa5db,0xacb03000,0xa7653000,0x2d7226a1,0xaf1aa814,0x2fafa934,0x2d00af30,0x2b5eafed,
0x1648afbc,0x2c87affc,0x2e992934,0xa9f1ac07,0xac322faf,0xaf8028d5,0xaaaaae1f,0xae7c2faf,0x2f1aad72,0xa30e2ed0,0xa30e2fe6,0x2e1f1cb6,0xaffc26a1,0x2fedadba,0x2cd8af6e,0x2b05afd4,
0xad27ac32,0xa30ead72,0x2faf9cb6,0xad27a515,0x1fd92f6e,0xafbc2e99,0xacd8ac87,0xad4d3000,0x2c5dafbc,0x2a4e2b05,0x16482f91,0x2eb5a44e,0xaf802d00,0x2ed0afa0,0x2cb0afa0,0x2aaaafaf,
0xafe626a1,0xaddc1648,0x2fffaa4e,0xaed026a1,0x2d002c07,0xad272ffc,0xae1fa934,0xabb72fbc,0x1fd9afa0,0x2e5ea30e,0x244e2f02,0x2f30a8d5,0xadba2f46,0x2c87afe6,0x2c87afc9,0x2a4eaf80,
0xafff2d96,0xae7c2c5d,0xafc92c5d,0x2d72a9f1,0xa17e2dfe,0xaff42fbc,0xa8752ee9,0x2ff8af30,0x2fedad00,0xad4d2f1a,0x2f91ab5e,0x2e5eafaf,0x25dbae7c,0x16482993,0x29f1af46,0x25dbac32,
0xae3f2fff,0xaff82fc9,0xaff82e7c,0x2f02ad72,0x2c0725db,0xadfe2f5a,0x9fd92d96,0x2fedafdd,0x2f6eaf91,0xa6a12c07,0x2fd4acd8,0x2dbaaf30,0xa765ab5e,0x2aaaa30e,0x2993af02,0x2515ab5e,
0xa5db2dfe,0xad962ee9,0xaf5a2fbc,0x2fddaf30,0x2f46ab5e,0xa7652bb7,0x25152bb7,0x2f80aff8,0x2d00afc9,0x28d59cb6,0x2ff8addc,0x2d00ae7c,0xacd89648,0x2dfeac5d,0x2934aeb5,0x244eaa4e,
0x2c07217e,0x9fd92875,0xadfe2ff4,0x2fedaff8,0x2fddaf46,0x29f1a515,0x29f12765,0x2eb5af80,0x2515ad96,0x2ddcac87,0x2fffaeb5,0x2c32ad96,0xaf022b05,0x2fa0aee9,0x28d5ae5e,0x230ea934,
0x2f91ad00,0x2cd8ab5e,0xac072f1a,0x2f30afaf,0x2d96afc9,0x2eb5addc,0x2c879cb6,0x2d96ae7c,0xa993a6a1,0x2fc9af5a,0x2fe6af5a,0x2aaaac87,0xaff82e5e,0x2ff4affc,0x2875adfe,0x217ea814,
0x2f6eafed,0x2fd4af91,0xa6a12d4d,0x2dbaae5e,0x2515ad00,0x2fffaff8,0x2ddca8d5,0x2c32ad00,0xae1f2993,0x2fafafe6,0x2fafafc9,0x28d5aaaa,0xaf912fdd,0x2ee9af5a,0x2814ad96,0x1fd9a5db,
0x2b5eae7c,0x2f02af46,0x230e2993,0x2b5eac32,0xab059648,0x2e5eaeb5,0x2ee9ac5d,0x2934aa4e,0xafdd2e5e,0x2d96adfe,0x2f5aaffc,0x25dba814,0xaddc2faf,0x2cb0ad27,0x2765ad27,0x1cb6a30e,
0xa765a5db,0x2993a9f1,0x2aaa9648,0x2515a5db,0xaf022cd8,0x28d5a934,0x2fa0adfe,0x230ea44e,0xaf912ff8,0x2814a875,0x2ee9aff4,0x1fd9a17e,0xaa4e2ddc,0x26a1a765,0x26a1acb0,0x16489cb6,
0x2d722d96,0x25152c5d,0x2c322c5d,0x1cb6a9f1,0x2d272d4d,0xad00a814,0x2bb72c07,0x2e1f2b05,0x2cd82d00,0xaffcaf1a,0x2b052b5e,0x2fed2faf,0x2c872cb0,0xadbaaf80,0x2a4e2aaa,0x2c872ed0,
0x2e3f2ddc,0x2ff82ed0,0x2ff82fe6,0xaf02afff,0x2ee92e99,0x2d4d2f6e,0x2ffc3000,0xa44eac87,0x2f6e2f30,0xa6a12814,0x2fd42fed,0x2dba2934,0x2fc92fa0,0xaf46ad00,0x2f802faf,0x2fe62fa0,
0xac87ad4d,0x9648ac07,0x29f12814,0xae99ab05,0xa993ab5e,0x2ed02bb7,0x2cb02bb7,0xaf46aff8,0xa30ea765,0x2f1a2fff,0x2e1f2d72,0xa30eacb0,0x244e1648,0x1fd92c5d,0x2f302eb5,0x2e5e2a4e,
0xaee9ae1f,0xaffcaf02,0xad4dae3f,0x244e2d27,0xafddaf80,0xa9f1ae7c,0xa9f1ac32,0xaeb5aaaa,0xafe6b000,0x2d7225db,0x9cb6a6a1,0xaed0b000,0xaf02af91,0x2fa02fbc,0x28d5244e,0x230eab05,
0x2b052d00,0xa44e2b5e,0xafbcaf1a,0x2f912faf,0x16482765,0xafd4ad72,0xafddafff,0x16482cb0,0xaaaaa6a1,0xac32af5a,0xae7caf5a,0xaf80ac87,0xae1facd8,0x2d001fd9,0xabb7ad4d,0xad27afbc,
0x2f6e2e5e,0x2fd42f30,0xa6a11fd9,0x2dba244e,0x2fe62ff4,0x1cb62d27,0xad72ab5e,0x2ed02ff4,0x2e1f2f46,0xafafacb0,0xafafaed0,0xa8d52993,0x29342c87,0xac07af6e,0xafbcb000,0xaffcae99,
0xa8d5acb0,0x2875aaaa,0x2e3f2f80,0xa8d5aed0,0x29341648,0x2fed2eb5,0x28142c5d,0x2f302a4e,0x2e992cd8,0x16482d4d,0xa9f19fd9,0x2c872fbc,0x2fff2faf,0xafe6ad27,0xaed0ad27,0xaddca30e,
0xafc9ae99,0xaf80af5a,0x2f462d96,0xafe6ae99,0xaf02afed,0x28d5ab05,0x2fa02ffc,0x230eacd8,0xa934ad27,0x2fbc2f02,0x2c072e3f,0x2ffc2e1f,0x2a4e1cb6,0xa6a12c32,0xa6a12515,0x96482d72,
0xaaaa29f1,0xaed025db,0xacb025db,0x2f801648,0xaf1aaf91,0x2875ae5e,0xae3fafed,0xab5e2d4d,0x2c07a875,0x2b052ff8,0x2d4da17e,0xa814aff4,0x2eb52fc9,0xaf6ead72,0x2dba2fff,0x2eb52e7c,
0x2f022f80,0x2b5e2fe6,0x2b5e2fc9,0x230eaf46,0xacd826a1,0xaf30ad96,0xaf91a9f1,0x2c072fd4,0xad96affc,0x2fdd244e,0xa5dbaee9,0xaf5aad4d,0x2e7c217e,0xad722bb7,0x2fff2d00,0x2fc9217e,
0x2c5da934,0x2f5aa44e,0x30002cd8,0xaeb5adfe,0x2d722ff8,0xacb02d00,0xa7652d00,0x2fff28d5,0xaf02a515,0x217eaf80,0xaf1aaf46,0xaf022765,0xa814af5a,0x2b052fdd,0x2d4da5db,0x2c07ad96,
0xae5eafa0,0xa934aff4,0x2b05abb7,0xaee928d5,0x2eb51cb6,0x2d962ed0,0x2d962fe6,0x2c87ad72,0x27652f6e,0xaf80ac5d,0xaf46a5db,0xa5152f6e,0xaff4ad4d,0x2ff8244e,0xa17eaee9,0xa875affc,
0xad4d2875,0xafbc217e,0xacd8aff8,0x1fd92ff4,0xaa4eafe6,0x2e99aaaa,0x2fd42993,0xaa4eafc9,0x2fff2c87,0xacb02d96,0xa7652d96,0x2d722eb5,0xab5e2c07,0x2875af30,0xae3faf91,0xaf1aacd8,
0x2d962fbc,0x25db2ffc,0xafdda934,0x2f5a2c07,0xafc9a875,0xaaaaafa0,0x2993ad27,0xafe6a875,0x28d5ad72,0x2d002ed0,0x2d002fe6,0x2ff81cb6,0x2d4d2fd4,0xae5ead96,0xafeda9f1,0xaf9126a1,
0x2e1fa765,0x2ff49cb6,0xa8752ddc,0x2e1facb0,0x1fd92f5a,0xafbc25db,0xacd8afdd,0xad4d2d96,0xaeb5aee9,0x2f5aa934,0x30002b05,0x2c5dae5e,0x2f80230e,0xaed02b5e,0xacb02b5e,0xaaaa2f02,
0xacb0afd4,0x9cb6b000,0x2ddc2f5a,0xa765afd4,0x2ff42c07,0x217e2ffc,0xaff8a934,0x28752fbc,0xadfe28d5,0xa44eaff4,0x2cd8abb7,0xa934afa0,0x1648af46,0x25db2fe6,0x25db2fc9,0x29f12f80,
0xafff9648,0xae7ca6a1,0xafc9a6a1,0x2d722a4e,0x2ff81fd9,0x230e2ee9,0x2faf2814,0x217eaf91,0xafeda30e,0x2d4dafa0,0xaf91a8d5,0xae5e2f02,0x2fdd2515,0xb0002aaa,0x2f6e2993,0x2fdda765,
0xa30e2fff,0xad272fc9,0xad272e7c,0x2fafad72,0x2814afdd,0x2ffcaa4e,0x2dfeadba,0xae5ea5db,0xaa4e2f91,0xac5dac07,0xaeb52cd8,0x96482f30,0x2c32af1a,0xa9932ff4,0x2f46abb7,0x2e7caf1a,
0x2fdd1fd9,0x2dba2814,0x2a4e2ee9,0x25dbaf91,0xaf46a8d5,0x2765afaf,0xa515afaf,0xaf802e1f,0x2e3f2c32,0xafa02ddc,0xa17e2fff,0x2e3f2515,0xacd8adba,0x2dfe26a1,0x2934afd4,0x244eaf6e,
0x2814aff8,0x2dfeafaf,0x2ffca30e,0xae5ea17e,0xac872f46,0xaf5a2515,0xaf5aa765,0xa6a12f80,0x2e7cadba,0x1cb62e99,0x2ddc2c5d,0x2fc9adba,0xafaf2b05,0x2f1aaee9,0xab5eae5e,0xad00a934,
0xaf91a30e,0xacd8a8d5,0x2c07afa0,0xaf302f02,0x2dba2c32,0xac5d2fff,0xae992ddc,0x2dba2515,0xa993aeb5,0x2fc9a9f1,0x2fe6a9f1,0x2aaaafdd,0xa17e2fed,0xa30eadfe,0xafaf9fd9,0xaff82c07,
0xaa4e2fed,0xaeb52f91,0xac5dad4d,0x96482e5e,0x2e7cae3f,0x2ddc217e,0x1cb62fa0,0x2fc9ae3f,0xaff82993,0x2bb7afe6,0x2bb7afc9,0xab5eaaaa,0x2f3025db,0xafbc2a4e,0xaee92dba,0xadfe2fdd,
0x2f1a2515,0x2bb72993,0xaff42aaa,0x2f1aa765,0xab05adba,0x2e5eafd4,0x2ee926a1,0x2934af6e,0xa5db2fed,0xadba9fd9,0xaa4eadfe,0xafdd2c07,0x2ddcaf02,0xacb02ff8,0xa7652ff8,0x9cb62e3f,
0x2c32afdd,0x2f46af6e,0xa9933000,0x2e7cafdd,0xafaf2cd8,0xab5ea934,0x2f1aadfe,0xad00a44e,0x2f30217e,0xaee92faf,0xafbc230e,0xadfe2ff8,0xa9f1addc,0x2c5d2765,0x2c5d2cb0,0x2d961cb6,
0xa993aa4e,0x2765ac87,0xa515ac87,0xaaaa2dba,0xafa02f30,0xabb7244e,0xaff42e5e,0x28d51fd9,0x28142bb7,0xaf912e1f,0x1fd92d27,0x2ee9ad00,0x2fd4aed0,0xaf5a2fff,0x3000addc,0x2fd4afe6,
0xafaf2f46,0xafa02e7c,0xafa02c32,0x2d00a993,0x244e2c5d,0xaf913000,0xab052f5a,0x2fbcaeb5,0x3000adfe,0xac872e5e,0x2e99a814,0x2f6eaffc,0x2515ae1f,0x1cb62875,0x2d72aff4,0x2c32ae1f,
0x26a12b05,0xa9f12cd8,0xad962fed,0x2fd4affc,0x2fffae1f,0x2515230e,0x2c32230e,0x2ddcaf1a,0x2875ae7c,0x2d27aaaa,0x2fa0af80,0x2875ac32,0xaee929f1,0x2f91ae99,0x9fd9ac87,0xa8149648,
0x2fedaf1a,0x2f30ae3f,0x29342875,0x2814ab5e,0x26a1addc,0x3000afc9,0x3000ae7c,0xa5db9cb6,0xaed02a4e,0x2f46afd4,0x2993ae99,0xacb02a4e,0xae3f2ffc,0x2d27ae5e,0xae1f2814,0xaf022dfe,
0x9fd9abb7,0x2c07ad27,0x2fedae1f,0xadfe2d00,0xaf6e2cb0,0x25dba993,0x2c5daf46,0xaf6e2ed0,0xaddc2fdd,0xa5159648,0xac329648,0xafff2fd4,0x28d52814,0xabb72934,0xaff42f30,0xafa02fed,
0xb0002ee9,0xae992dfe,0x2c87af30,0xaf6e2fbc,0xac322f02,0xaf802f1a,0xaaaaa17e,0xae7c2f02,0x2b5e1cb6,0xaff42fc9,0xaff42e7c,0xad272ddc,0x2ffcaeb5,0xafed3000,0xacd82f5a,0xab052c5d,
0xa17e2c32,0xad002d72,0xabb71cb6,0xa17e2515,0x2dfea9f1,0xac072c87,0xafed2e99,0x1fd91648,0x2fd4afbc,0xa9f12b05,0xad962f91,0x26a1a44e,0x2aaaae3f,0xa76528d5,0x251528d5,0x2993a875,
0x2fe6aeb5,0x2ddcadba,0xafff2f6e,0x2ed0aeb5,0x2e3fafbc,0x2e1fadfe,0xad272f30,0x2f02aee9,0x1fd9ab5e,0x2e5eae3f,0x244e2875,0x2f30af1a,0xad962993,0x2e99ae7c,0x2e99ac32,0x2f5aaf46,
0x299329f1,0xa76525db,0x251525db,0x2aaa1648,0x28d52934,0xaf02acd8,0x230e244e,0x2fa02dfe,0x28142875,0xaf91aff8,0x1fd9217e,0x2ee92ff4,0x26a12765,0xaa4eaddc,0x16481cb6,0x26a12cb0,
0x2f022f46,0x2b5e2e7c,0x2b5e2c32,0x230ea993,0x2e5e2eb5,0xab051648,0x29342a4e,0x2ee92c5d,0x2d962dfe,0xafddae5e,0x25db2814,0x2f5a2ffc,0x2cb02d27,0xaddcafaf,0x1cb6230e,0x27652d27,
0x2fd42f91,0x2f6e2fed,0x2dba2e5e,0xa6a1ad4d,0x2fff2ff8,0x25152d00,0x2c322d00,0x2ddc28d5,0x2faf2fe6,0xae1fa993,0x28d52aaa,0x2faf2fc9,0x2ee92f5a,0xaf91afdd,0x1fd925db,0x28142d96,
0x2cd82b5e,0x2f912d00,0x2f302faf,0xac07af1a,0x2eb52ddc,0x2d962fc9,0x2d962e7c,0x2c871cb6,0x2fc92f5a,0xa99326a1,0x2aaa2c87,0x2fe62f5a,0x2ff42ffc,0xaff8ae5e,0x217e2814,0x28752dfe,
0x9fd9a875,0x2c07a17e,0x2fed2ff8,0xadfeaff4,0x29f12515,0x2fdd2f46,0x2eb52f80,0x29f1a765,0x2ddc2c87,0x25152d96,0x2c322d96,0x2fff2eb5,0x2fa02ee9,0xaf02ab05,0x230e2934,0x28d52e5e,
0xad96aee9,0xa5dbadfe,0x2fdd2f30,0xaf5aafbc,0xa765abb7,0x2f462b5e,0x2f802ff8,0x2515abb7,0x28d51cb6,0x2d002fc9,0x2d002e7c,0x2ff82ddc,0x2dfe2c5d,0xacd81648,0x244e2a4e,0x29342eb5,
0xaff8afc9,0xae3fafff,0x2f022d72,0xaff8ae7c,0xadfeaf5a,0x2c07a5db,0x2fed2fdd,0x9fd9ad96,0xa6a1ac07,0x2f6e2f91,0x2dba2f30,0x2fd42cd8,0x2aaa230e,0xa7652b5e,0x25152b5e,0x29932f02,
0xae7cac5d,0xafffad96,0x2d7229f1,0xafc9ac5d,0xaff4afbc,0xa17eadfe,0x2ff82f30,0xa875aee9,0xad4daf1a,0x2fed2d00,0x2e5e2faf,0x2f912b5e,0x1648a993,0x25db2e7c,0x25db2c32,0x29f12f46,
0xaddc9648,0xafe6a6a1,0xaed0a6a1,0x2fff2a4e,0xad27affc,0x2d00ac07,0xabb7afbc,0xae1f2934,0x2e5e230e,0x1fd92fa0,0x2f3028d5,0x244eaf02,0x2c872fe6,0xadbaaf46,0x2a4e2f80,0x2c872fc9,
0xa30e2d72,0xad272c32,0xad272515,0x2faf1cb6,0xafbcae99,0x1fd9af6e,0xad4db000,0xacd82c87,0x2a4eab05,0x2c5d2fbc,0x2eb5244e,0x1648af91,0x2ed02fa0,0xaf80ad00,0x2aaa2faf,0x2cb02fa0,
0x2c872ffc,0x16482fbc,0xa9f12c07,0x2e99a934,0xaf80a8d5,0xac32afaf,0xae7cafaf,0xaaaa2e1f,0xa30eaed0,0x2f1a2d72,0x2e1f9cb6,0xa30eafe6,0x2fed2dba,0xaffca6a1,0x2b052fd4,0x2cd82f6e,
0x2fbc2e1f,0x2d4d2f02,0x9fd92e3f,0x2cd8ad27,0xac872993,0xaf5aacb0,0xaf5aaed0,0xa6a12f46,0xacb0b000,0x2fff25db,0x2d72a6a1,0xa765b000,0x2faf2934,0xaf1a2814,0x2b5e2fed,0x2d002f30,
0x2f30230e,0x2fed28d5,0x28142fa0,0x2934af02,0x16482ed0,0xafd41cb6,0xafddad72,0x16482fe6,0xaf46aeb5,0x2ed0a9f1,0x2cb0a9f1,0xa993afdd,0x2e1fa44e,0xad002d4d,0x2bb72ffc,0x2d272ee9,
0x2a4eacd8,0x2eb5ab05,0x2c5d2ffc,0x1648afed,0x2cb02ff4,0xad722d27,0xafffab5e,0x27652ff4,0xaff8aaaa,0x2bb7ae7c,0x2bb7ac32,0xab5eaf80,0x2b05ac87,0xa8142f6e,0x2c073000,0x2d4d2e99,
0xa8d5afe6,0x2875af80,0x2e3f2f46,0xa8d5afc9,0x2f912dba,0xa44e2fd4,0xafbca6a1,0x2b052f6e,0xae99244e,0x9648affc,0x29f1ad4d,0xac87aee9,0x1cb6af02,0x25152ff8,0x2c322ff8,0x2d722e3f,
0xaed0ae99,0xaaaaaf5a,0x2f802d96,0xacb0ae99,0x2faf244e,0x2b5e2f30,0xaf1a1fd9,0x2d002e5e,0xab052d27,0xac07af02,0x2814ae3f,0xad4dae1f,0xa9f1afff,0x2c5d2ed0,0x2c5d2fe6,0x2d962ddc,
0xaf46aa4e,0xac32ac87,0xae7cac87,0x29932dba,0x2f1a2b05,0xa8752fed,0x2e3f2cd8,0x2b5eaffc,0xaee9abb7,0x2f30ae1f,0xadfead27,0xafbc2d00,0x2eb52c32,0xaf6e1cb6,0x2dba2d72,0x2eb52515,
0xafaf2993,0xafa02515,0xafa0a765,0x2d002aaa,0x2feda6a1,0x29342d96,0x2f3029f1,0x2814afd4,0xb0001fd9,0x2c87afed,0xae99ac07,0xaf6e2dfe,0x2fe6217e,0xafff2bb7,0x2ddc2d00,0x2ed0217e,
0xac5d2f30,0xaf5a2e5e,0xb000244e,0x2eb51fd9,0x2ddcae1f,0x2e7c230e,0x2fc9230e,0x1cb6af1a,0xaf022cb0,0x217eaf46,0xaf1aa993,0xaf022ed0,0x2fbca9f1,0xaf302e99,0x2dfe2c87,0x2ee91648,
0x244e2fa0,0xab052ff4,0xaf912bb7,0x2fbca8d5,0x26a1afff,0x3000ac32,0x3000a515,0xa5dbaddc,0xac322f6e,0xaaaaac5d,0xaf80a5db,0xae7c2f6e,0x2e3fadfe,0xad272fed,0x2e1f2c07,0x2f029fd9,
0x2dfe2bb7,0x28142d27,0xae5e2e1f,0x2ffcad00,0xaa4eae7c,0x2e99af80,0x2fd4aaaa,0xaa4eac32,0x9cb62fdd,0xae7c9648,0xafc99648,0xaddc2fd4,0x2b5eafbc,0xa8752f91,0x2e3f2b05,0x2f1aa44e,
0x3000a814,0x2e999fd9,0xac872f91,0x2f6eaee9,0xaed0a875,0x2993afa0,0x2f46ad27,0xacb0a875,0x2b5e2ddc,0xaff42c32,0xaff42515,0xad272fff,0x1fd9afd4,0x244e2d96,0x2e5e29f1,0x2f30a6a1,
0x2e1faed0,0x2ff4addc,0xa8752fff,0x2e1fafe6,0xaffc29f1,0xa814ac87,0x2e5eae99,0xadfe9648,0x2eb52814,0xaf5a2f30,0xb0002934,0xac5d2fed,0xa993ae3f,0x2c3228d5,0x2e7c28d5,0x2f46a875,
0x2515afd4,0x2d72b000,0x1cb62f5a,0x2c32afd4,0xae3f2ee9,0xae1f1fd9,0x2d27af91,0xaf022814,0x2ffca8d5,0xacd82ff4,0xafed2bb7,0xab052fa0,0xad96aaaa,0x2e99a515,0x2e992765,0x2f5aa993,
0x1cb6adba,0x2cb0aeb5,0x2765aeb5,0xaddc2f6e,0xaff82d4d,0xa30ea814,0xafaf2c07,0xa17e2b05,0xa44e2e3f,0xadfe2b5e,0xa9342f1a,0x2cd8a875,0x2fddacb0,0xb0002f80,0x2f6eaaaa,0x2fddaed0,
0xad009cb6,0xa17ea765,0xa17eacb0,0xabb72ddc,0xaee92fdd,0xad4d2a4e,0xaffc2dba,0x244e25db,0x29f12934,0xafd42ee9,0xa6a12e5e,0x2d96ab05,0x2fc9af1a,0xaf462ff4,0x2f80abb7,0x2fe6af1a,
0xafdd2d4d,0xadba2c07,0xaa4ea814,0xa5db2b05,0xaaaa2f1a,0xafc92f02,0xafe62f02,0x2993a17e,0x2e3fa765,0xafa02fff,0xa17e2d72,0x2e3facb0,0x2e5eb000,0xad4d2eb5,0x2f91ac5d,0x2fedaf5a,
0xaee92ff8,0xaffc2faf,0xad4d230e,0x244e217e,0x25db2aaa,0xaf6e2fe6,0xaf6e2fc9,0x2c5da993,0x2fe6adba,0xad722e99,0x1cb62c5d,0x2ed0adba,0x2bb7af30,0xa8d52c07,0x2fa0acd8,0x2ff4af91,
0xa9342e3f,0xae5e2f1a,0xaee92b5e,0x2b05a875,0x2dbaa765,0xac5d2d72,0xae992fff,0x2dbaacb0,0x2f80afd4,0xa7652a4e,0x25152a4e,0x2f46ae99,0x217eacd8,0x230e1fd9,0x2fafad4d,0x2ff8afbc,
0x29f1244e,0xa6a12934,0xafd42dfe,0x2d96acd8,0x2fe6ae3f,0x1cb6217e,0xad722fa0,0x2ed0ae3f,0x2d27af80,0x2875a515,0x28752765,0x2fa0af46,0xa934a5db,0x2c07aa4e,0x2fbcadba,0x2ffcafdd,
0x2f1aacb0,0x2bb7aaaa,0xaff42f80,0x2f1aaed0,0x2f30b000,0x2cd8ac5d,0xac072eb5,0x2f91af5a,0x25dbacd8,0x2dbaad4d,0x2a4e1fd9,0x2fddafbc,0xad722875,0x2e7cae1f,0x2fc9ae1f,0x2fffaff4,
0x2fc9afdd,0x2f80af6e,0xaf463000,0x2fe6afdd,0x2bb7ae5e,0x2fa0af91,0xa8d52d4d,0x2ff4afed,0xa934a17e,0x2fbcafaf,0x2c07a30e,0x2ffcaff8,0xaf5a2d72,0x2fd4afc9,0x2fd4ae7c,0x3000afff,
0x9d4d9e16,0xada6ae7d,0x9b769c84,0xabf0accf,0x985299e4,0xa897aa43,0x90b6957f,0xa102a5d8,0x13db0a48,0x242c1aad,0x191b1712,0x296d2783,0x1c201aad,0x2c632b1a,0x1db21ce9,0x2e112d3a,
0xa3f4a491,0xae51af42,0xa199a2c6,0xac70ad60,0x9e7ba06b,0xa922ab00,0x97129c20,0xa199a688,0x19e410b6,0x24aa1b76,0x1fa81d4d,0x2a112833,0x222f2102,0x2ce82bf0,0x2445235d,0x2ec92dd8,
0xa6a1a79c,0xaefcb004,0xa4aaa5a5,0xace8adf2,0xa166a35d,0xa9acabbe,0x99e49edf,0xa22fa738,0x1ce913db,0x25281c20,0x2262206b,0x2ab528a4,0x2528242c,0x2d6d2c63,0x271f2623,0x2f822e77,
0xa8a4a954,0xafa8b067,0xa688a7e8,0xad60ae84,0xa38fa528,0xaa37ac3d,0x9c20a0d0,0xa2c6a7e8,0x1edf157f,0x25a51c84,0x2478222f,0x2b592915,0x273825d8,0x2df22ccf,0x28fc284c,0x301d2f16,
0xa9f8aadb,0xb02ab0ca,0xa833a915,0xadd8af16,0xa4dca6a1,0xaac1ac9c,0x9d4da22f,0xa35da84c,0x206b1712,0x26231ce9,0x25bf23f4,0x2bfd2987,0x28a42783,0x2e772d3a,0x2a692987,0x307a2fb5,
0xab4cac31,0xb081b12e,0xa922aa37,0xae51afa8,0xa5f1a80d,0xab4cacfb,0x9e7ba38f,0xa3f4a8a4,0x21661852,0x26a11d4d,0x270524dc,0x2c5029f8,0x29ac2897,0x2efc2da6,0x2bd72ac1,0x30d7302a,
0xac50acf5,0xb0d7b192,0xaa11ab59,0xaec9b01d,0xa705a8ca,0xabd7ad5a,0x9fa8a478,0xa445a8fc,0x2262191b,0x271f1db2,0x282625bf,0x2ca22a69,0x2ab5296d,0x2f822e11,0x2ca22bfd,0x3135307a,
0xacfbadb9,0xb12eb1f7,0xab00ac3d,0xaf42b067,0xa80da987,0xac31adb9,0xa06ba528,0xa491a954,0x235d19e4,0x279c1e16,0x28ca26a1,0x2cf52adb,0x2bbe2a43,0x30042e7d,0x2d5a2c9c,0x319230ca,
0xb185b25c,0xb426b4cc,0xafbbb0b1,0xb1c6b306,0xac76ae18,0xaea3b08a,0xa4dca9ac,0xa738ac37,0x280d1e7b,0x2a0520d0,0x2d472b4c,0x2fdb2d6d,0x30472ee9,0x32663128,0x31f0311b,0x347933a8,
0xb1ddb2c1,0xb453b501,0xb01ab0fb,0xb204b352,0xacbcae77,0xaee9b0ba,0xa528aa05,0xa783ac63,0x284c1edf,0x2a432102,0x2d992bbe,0x30172da6,0x308a2f55,0x32aa315f,0x324f316b,0x34aa33fc,
0xb235b327,0xb481b537,0xb057b145,0xb242b39e,0xad01aed6,0xaf2fb0eb,0xa573aa5d,0xa7cfac90,0x288b1f44,0x2a822134,0x2deb2c18,0x30412ddf,0x30ce2fc2,0x32ef3196,0x32ae31bc,0x34db3428,
0xb28db38e,0xb4afb56d,0xb094b18f,0xb280b3eb,0xad47af36,0xaf75b11b,0xa5bfaab5,0xa80dacbc,0x28ca1fa8,0x2ac12166,0x2e3e2c50,0x306a2e18,0x31113017,0x333531cd,0x330d320e,0x350d3452,
0xb2e5b3f5,0xb4ddb5a3,0xb0d1b1da,0xb2beb41c,0xad8caf95,0xafbbb14b,0xa60aab0d,0xa833ace8,0x29092006,0x2b002199,0x2e902c89,0x30942e51,0x3155304d,0x337a3204,0x336d325f,0x3540347c,
0xb33eb42e,0xb50cb5da,0xb10eb224,0xb2fcb443,0xadd2aff5,0xb001b17c,0xa655ab65,0xa859ad14,0x29482039,0x2b4021cb,0x2ee32cc2,0x30be2e8a,0x31993084,0x33c0323b,0x33cd32b1,0x357234a6,
0xb398b463,0xb53ab612,0xb14bb26f,0xb33bb469,0xae18b02a,0xb024b1ac,0xa6a1abbe,0xa87ead40,0x2987206b,0x2b7f21fd,0x2f362cfb,0x30e72ec3,0x31dd30ba,0x34033273,0x34173303,0x35a534d1,
0xb3f2b497,0xb569b64a,0xb189b2bb,0xb37ab490,0xae5eb05a,0xb047b1dd,0xa6ecac0b,0xa8a4ad6d,0x29c6209d,0x2bbe222f,0x2f882d34,0x31112efc,0x322130f1,0x342632aa,0x34483356,0x35d934fc,
0xb599b682,0xb722b82e,0xb3b9b4b7,0xb4ddb5f9,0xb06ab20e,0xb185b398,0xa8caad99,0xa9f8aefc,0x2bfd2262,0x2cfb23f4,0x313b2f36,0x328d3081,0x344932e2,0x35693453,0x360d3527,0x37bd368b,
0xb5c9b6bb,0xb755b84d,0xb3f8b4df,0xb4feb622,0xb08db23e,0xb1a9b3ca,0xa8f0adc5,0xaa1eaf29,0x2c1e2294,0x2d1b2413,0x31652f6f,0x32b7309d,0x346d331a,0x358e3470,0x36413553,0x37f536ba,
0xb5f9b6f5,0xb789b86d,0xb41cb506,0xb51fb64c,0xb0b1b26f,0xb1cdb3fc,0xa915adf2,0xaa43af55,0x2c3d22c6,0x2d3a242c,0x318f2fa8,0x32e230ba,0x34903352,0x35b3348d,0x3676357e,0x381736e8,
0xb629b72f,0xb7bdb88d,0xb43cb52e,0xb540b676,0xb0d4b2a1,0xb1f0b417,0xa93bae1e,0xaa69af82,0x2c5d22f9,0x2d5a2445,0x31b92fe2,0x330d30d7,0x34b4338b,0x35d934aa,0x36ab35ab,0x38343717,
0xb65ab76a,0xb7f1b8ad,0xb45cb556,0xb561b6a0,0xb0f7b2d2,0xb214b430,0xa961ae4b,0xaa8fafaf,0x2c7d232b,0x2d79245f,0x31e3300e,0x333830f4,0x34d833c3,0x35fe34c7,0x36e035d7,0x38513746,
0xb68bb7a5,0xb813b8ce,0xb47cb57e,0xb582b6ca,0xb11bb303,0xb238b449,0xa987ae77,0xaab5afdb,0x2c9c235d,0x2d992478,0x320e302a,0x33633111,0x34fc33fc,0x362434e4,0x37173604,0x386f3775,
0xb6bdb7e2,0xb82eb8f0,0xb49cb5a7,0xb5a3b6f5,0xb13eb335,0xb25cb463,0xa9acaea3,0xaadbb004,0x2cbc238f,0x2db92491,0x32383047,0x338e312e,0x3520341a,0x364a3501,0x374d3631,0x388d37a5,
0xb6efb80f,0xb849b911,0xb4bdb5d0,0xb5c5b720,0xb162b366,0xb280b47c,0xa9d2aed0,0xab00b01a,0x2cdb23c2,0x2dd824aa,0x32623064,0x33b9314b,0x35453437,0x3670351f,0x3785365e,0x38ab37d6,
0xb865b934,0xb94dba5c,0xb5e7b74c,0xb6fcb85a,0xb2a4b495,0xb3c6b564,0xab26b031,0xac2bb0e4,0x2df824c3,0x2ef6258c,0x33e43168,0x34a13252,0x3697353c,0x37d4362d,0x38ca3803,0x39d038d0,
0xb880b957,0xb96bba84,0xb609b777,0xb720b872,0xb2c8b4af,0xb3ebb57e,0xab4cb047,0xac3db0fb,0x2e1824dc,0x2f1625a5,0x34083185,0x34b7326f,0x36bd355a,0x37fd364c,0x38e9381c,0x39f338eb,
0xb89cb97a,0xb98abaad,0xb62bb7a4,0xb744b88a,0xb2ecb4c9,0xb408b599,0xab72b05d,0xac50b111,0x2e3724f5,0x2f3625bf,0x341e31a2,0x34ce328d,0x36e43577,0x3813366b,0x39093835,0x3a173906,
0xb8b9b99e,0xb9aabad7,0xb64db7d0,0xb768b8a2,0xb310b4e2,0xb41ab5b3,0xab98b074,0xac63b128,0x2e57250f,0x2f5525d8,0x343331c0,0x34e432aa,0x370b3595,0x3828368a,0x3929384e,0x3a3b3922,
0xb8d6b9c3,0xb9cabb02,0xb670b7fd,0xb78cb8ba,0xb335b4fc,0xb42db5ce,0xabbeb08a,0xac76b13e,0x2e772528,0x2f7525f1,0x344931dd,0x34fa32c8,0x373335b3,0x383d36a9,0x39493868,0x3a60393e,
0xb8f3b9e8,0xb9ebbb2d,0xb693b815,0xb7b1b8d2,0xb359b516,0xb43fb5e9,0xabe3b0a1,0xac89b155,0x2e972541,0x2f95260a,0x345f31fa,0x351132e5,0x375b35d2,0x385236c8,0x396a3881,0x3a86395a,
0xb910ba0e,0xba0cbb59,0xb6b6b82c,0xb7d6b8eb,0xb37db530,0xb452b604,0xac05b0b7,0xac9cb16b,0x2eb6255a,0x2fb52623,0x34753217,0x35273303,0x378335f0,0x386836e8,0x398c389b,0x3aac3977,
0xb92eba35,0xba2dbb87,0xb6d9b843,0xb7fbb904,0xb3a2b54a,0xb464b61e,0xac18b0ce,0xacafb182,0x2ed62573,0x2fd5263c,0x348b3235,0x353e3321,0x37ab360e,0x387d3708,0x39ae38b6,0x3ad33994,
0x9ce99db2,0xad3aae11,0x9aad9c20,0xab1aac63,0x9712991b,0xa783a96d,0x8a4893db,0x9aada42c,0x157f10b6,0x25d82102,0x19e41852,0x2a432897,0x1c841b76,0x2ccf2bf0,0x1e161d4d,0x2e7d2da6,
0xa35da445,0xadd8aec9,0xa102a22f,0xabf0ace8,0x9d4d9fa8,0xa833aa11,0x90b699e4,0x9b76a4aa,0x1c201712,0x26882199,0x206b1e7b,0x2b002922,0x22c62199,0x2d602c70,0x249123f4,0x2f422e51,
0xa623a71f,0xae77af82,0xa42ca528,0xac63ad6d,0xa06ba262,0xa8a4aab5,0x93db9ce9,0x9c20a528,0x1edf19e4,0x2738222f,0x235d2166,0x2bbe29ac,0x25a524aa,0x2df22ce8,0x279c26a1,0x30042efc,
0xa84ca8fc,0xaf16b01d,0xa5d8a738,0xaccfadf2,0xa22fa478,0xa915ab59,0x957f9edf,0x9c84a5a5,0x20d01c20,0x27e822c6,0x2528238f,0x2c3d2a37,0x27e82688,0x2e842d60,0x295428a4,0x30672fa8,
0xa987aa69,0xafb5b07a,0xa783a8a4,0xad3aae77,0xa3f4a5bf,0xa987abfd,0x9712a06b,0x9ce9a623,0x222f1d4d,0x284c235d,0x26a124dc,0x2c9c2ac1,0x29152833,0x2f162dd8,0x2adb29f8,0x30ca302a,
0xaac1abd7,0xb02ab0d7,0xa897a9ac,0xada6aefc,0xa4dca705,0xa9f8ac50,0x9852a166,0x9d4da6a1,0x238f1e7b,0x28a423f4,0x280d25f1,0x2cfb2b4c,0x2a372922,0x2fa82e51,0x2c312b4c,0x312e3081,
0xabfdaca2,0xb07ab135,0xa96daab5,0xae11af82,0xa5bfa826,0xaa69aca2,0x991ba262,0x9db2a71f,0x24781fa8,0x28fc2445,0x28ca2705,0x2d5a2bd7,0x2b592a11,0x301d2ec9,0x2cf52c50,0x319230d7,
0xac9cad5a,0xb0cab192,0xaa43abbe,0xae7db004,0xa6a1a8ca,0xaadbacf5,0x99e4a35d,0x9e16a79c,0x2528206b,0x29542491,0x2987280d,0x2db92c31,0x2c3d2b00,0x30672f42,0x2db92cfb,0x31f7312e,
0xb11bb1f0,0xb3a8b479,0xaee9b047,0xb128b266,0xab4cad47,0xad6dafdb,0x9e7ba80d,0xa0d0aa05,0x29ac24dc,0x2c372738,0x2e182c76,0x308a2ea3,0x30b12fbb,0x330631c6,0x325c3185,0x34cc3426,
0xb16bb24f,0xb3fcb4aa,0xaf55b08a,0xb15fb2aa,0xabbead99,0xada6b017,0x9edfa84c,0xa102aa43,0x2a052528,0x2c632783,0x2e772cbc,0x30ba2ee9,0x30fb301a,0x33523204,0x32c131dd,0x35013453,
0xb1bcb2ae,0xb428b4db,0xafc2b0ce,0xb196b2ef,0xac18adeb,0xaddfb041,0x9f44a88b,0xa134aa82,0x2a5d2573,0x2c9027cf,0x2ed62d01,0x30eb2f2f,0x31453057,0x339e3242,0x33273235,0x35373481,
0xb20eb30d,0xb452b50d,0xb017b111,0xb1cdb335,0xac50ae3e,0xae18b06a,0x9fa8a8ca,0xa166aac1,0x2ab525bf,0x2cbc280d,0x2f362d47,0x311b2f75,0x318f3094,0x33eb3280,0x338e328d,0x356d34af,
0xb25fb36d,0xb47cb540,0xb04db155,0xb204b37a,0xac89ae90,0xae51b094,0xa006a909,0xa199ab00,0x2b0d260a,0x2ce82833,0x2f952d8c,0x314b2fbb,0x31da30d1,0x341c32be,0x33f532e5,0x35a334dd,
0xb2b1b3cd,0xb4a6b572,0xb084b199,0xb23bb3c0,0xacc2aee3,0xae8ab0be,0xa039a948,0xa1cbab40,0x2b652655,0x2d142859,0x2ff52dd2,0x317c3001,0x3224310e,0x344332fc,0x342e333e,0x35da350c,
0xb303b417,0xb4d1b5a5,0xb0bab1dd,0xb273b403,0xacfbaf36,0xaec3b0e7,0xa06ba987,0xa1fdab7f,0x2bbe26a1,0x2d40287e,0x302a2e18,0x31ac3024,0x326f314b,0x3469333b,0x34633398,0x3612353a,
0xb356b448,0xb4fcb5d9,0xb0f1b221,0xb2aab426,0xad34af88,0xaefcb111,0xa09da9c6,0xa22fabbe,0x2c0b26ec,0x2d6d28a4,0x305a2e5e,0x31dd3047,0x32bb3189,0x3490337a,0x349733f2,0x364a3569,
0xb527b60d,0xb68bb7bd,0xb2e2b449,0xb453b569,0xaf36b13b,0xb081b28d,0xa262abfd,0xa3f4acfb,0x2d9928ca,0x2efc29f8,0x320e306a,0x33983185,0x34b733b9,0x35f934dd,0x36823599,0x382e3722,
0xb553b641,0xb6bab7f5,0xb31ab46d,0xb470b58e,0xaf6fb165,0xb09db2b7,0xa294ac1e,0xa413ad1b,0x2dc528f0,0x2f292a1e,0x323e308d,0x33ca31a9,0x34df33f8,0x362234fe,0x36bb35c9,0x384d3755,
0xb57eb676,0xb6e8b817,0xb352b490,0xb48db5b3,0xafa8b18f,0xb0bab2e2,0xa2c6ac3d,0xa42cad3a,0x2df22915,0x2f552a43,0x326f30b1,0x33fc31cd,0x3506341c,0x364c351f,0x36f535f9,0x386d3789,
0xb5abb6ab,0xb717b834,0xb38bb4b4,0xb4aab5d9,0xafe2b1b9,0xb0d7b30d,0xa2f9ac5d,0xa445ad5a,0x2e1e293b,0x2f822a69,0x32a130d4,0x341731f0,0x352e343c,0x36763540,0x372f3629,0x388d37bd,
0xb5d7b6e0,0xb746b851,0xb3c3b4d8,0xb4c7b5fe,0xb00eb1e3,0xb0f4b338,0xa32bac7d,0xa45fad79,0x2e4b2961,0x2faf2a8f,0x32d230f7,0x34303214,0x3556345c,0x36a03561,0x376a365a,0x38ad37f1,
0xb604b717,0xb775b86f,0xb3fcb4fc,0xb4e4b624,0xb02ab20e,0xb111b363,0xa35dac9c,0xa478ad99,0x2e772987,0x2fdb2ab5,0x3303311b,0x34493238,0x357e347c,0x36ca3582,0x37a5368b,0x38ce3813,
0xb631b74d,0xb7a5b88d,0xb41ab520,0xb501b64a,0xb047b238,0xb12eb38e,0xa38facbc,0xa491adb9,0x2ea329ac,0x30042adb,0x3335313e,0x3463325c,0x35a7349c,0x36f535a3,0x37e236bd,0x38f0382e,
0xb65eb785,0xb7d6b8ab,0xb437b545,0xb51fb670,0xb064b262,0xb14bb3b9,0xa3c2acdb,0xa4aaadd8,0x2ed029d2,0x301a2b00,0x33663162,0x347c3280,0x35d034bd,0x372035c5,0x380f36ef,0x39113849,
0xb803b8ca,0xb8d0b9d0,0xb53cb697,0xb62db7d4,0xb168b3e4,0xb252b4a1,0xa4c3adf8,0xa58caef6,0x30312b26,0x30e42c2b,0x349532a4,0x356433c6,0x374c35e7,0x385a36fc,0x39343865,0x3a5c394d,
0xb81cb8e9,0xb8ebb9f3,0xb55ab6bd,0xb64cb7fd,0xb185b408,0xb26fb4b7,0xa4dcae18,0xa5a5af16,0x30472b4c,0x30fb2c3d,0x34af32c8,0x357e33eb,0x37773609,0x38723720,0x39573880,0x3a84396b,
0xb835b909,0xb906ba17,0xb577b6e4,0xb66bb813,0xb1a2b41e,0xb28db4ce,0xa4f5ae37,0xa5bfaf36,0x305d2b72,0x31112c50,0x34c932ec,0x35993408,0x37a4362b,0x388a3744,0x397a389c,0x3aad398a,
0xb84eb929,0xb922ba3b,0xb595b70b,0xb68ab828,0xb1c0b433,0xb2aab4e4,0xa50fae57,0xa5d8af55,0x30742b98,0x31282c63,0x34e23310,0x35b3341a,0x37d0364d,0x38a23768,0x399e38b9,0x3ad739aa,
0xb868b949,0xb93eba60,0xb5b3b733,0xb6a9b83d,0xb1ddb449,0xb2c8b4fa,0xa528ae77,0xa5f1af75,0x308a2bbe,0x313e2c76,0x34fc3335,0x35ce342d,0x37fd3670,0x38ba378c,0x39c338d6,0x3b0239ca,
0xb881b96a,0xb95aba86,0xb5d2b75b,0xb6c8b852,0xb1fab45f,0xb2e5b511,0xa541ae97,0xa60aaf95,0x30a12be3,0x31552c89,0x35163359,0x35e9343f,0x38153693,0x38d237b1,0x39e838f3,0x3b2d39eb,
0xb89bb98c,0xb977baac,0xb5f0b783,0xb6e8b868,0xb217b475,0xb303b527,0xa55aaeb6,0xa623afb5,0x30b72c05,0x316b2c9c,0x3530337d,0x36043452,0x382c36b6,0x38eb37d6,0x3a0e3910,0x3b593a0c,
0xb8b6b9ae,0xb994bad3,0xb60eb7ab,0xb708b87d,0xb235b48b,0xb321b53e,0xa573aed6,0xa63cafd5,0x30ce2c18,0x31822caf,0x354a33a2,0x361e3464,0x384336d9,0x390437fb,0x3a35392e,0x3b873a2d,
0x214d2216,0x319b326c,0x1f762084,0x2fe830c8,0x1c521de4,0x2c962e40,0x14b6197f,0x250229d7,0x97db8e48,0xa82c9ead,0x9d1b9b12,0xad6bab82,0xa0209ead,0xb05eaf14,0xa1b2a0e9,0xb204b131,
0x27f32890,0x3241332b,0x259826c6,0x306a3156,0x227b246b,0x2d202efb,0x1b122020,0x25982a87,0x9de494b6,0xa8aa9f76,0xa3a8a14d,0xae0eac32,0xa62fa502,0xb0e1afe8,0xa845a75d,0xb2b6b1cc,
0x2aa02b9b,0x32e733e8,0x28aa29a5,0x30e131e5,0x2566275d,0x2daa2fb6,0x1de422df,0x262f2b36,0xa0e997db,0xa927a020,0xa661a46b,0xaeb0aca2,0xa927a82c,0xb163b05e,0xab1daa22,0xb368b266,
0x2ca22d52,0x338d3452,0x2a872be6,0x31563273,0x278f2927,0x2e333039,0x202024cf,0x26c62be6,0xa2df997f,0xa9a5a084,0xa877a62f,0xaf53ad13,0xab36a9d7,0xb1e5b0c8,0xacfaac4b,0xb40cb300,
0x2df52ed6,0x341834b0,0x2c322d13,0x31cc3300,0x28dc2aa0,0x2ebd3096,0x214d262f,0x275d2c4b,0xa46b9b12,0xaa22a0e9,0xa9bea7f3,0xaff5ad84,0xaca2ab82,0xb266b131,0xae65ad84,0xb464b399,
0x2f46302c,0x346a350c,0x2d202e33,0x3241338d,0x29f02c0c,0x2f4630f3,0x227b278f,0x27f32ca2,0xa5669c52,0xaaa0a14d,0xab04a8dc,0xb04badf5,0xadaaac96,0xb2e7b19b,0xafcfaebd,0xb4bcb418,
0x304b30ed,0x34bc3568,0x2e0e2f53,0x32b6340c,0x2b042cc8,0x2fcf3150,0x23a82877,0x28452cfa,0xa6619d1b,0xab1da1b2,0xac25a9be,0xb09cae65,0xaeb0ad6b,0xb368b204,0xb09caff5,0xb512b464,
0x30f331ad,0x350c35c4,0x2efb3039,0x332b3452,0x2c0c2d84,0x302c31ad,0x246b2927,0x28902d52,0xa75d9de4,0xab9ba216,0xacc8aaa0,0xb0edaed6,0xafb6ae40,0xb3e8b26c,0xb150b096,0xb568b4b0,
0x355d361e,0x37c63867,0x339f3497,0x359836b4,0x3071320a,0x32913473,0x28dc2daa,0x2b363032,0xac0ca27b,0xae01a4cf,0xb13eaf46,0xb3bdb163,0xb434b2d5,0xb627b506,0xb5beb4fa,0xb826b73e,
0x35ac3678,0x3808388f,0x340934dd,0x35cf36f5,0x30b53266,0x32d534a0,0x29272e01,0x2b82305e,0xac4ba2df,0xae40a502,0xb18eafb6,0xb406b19b,0xb473b33d,0xb663b539,0xb612b545,0xb84cb784,
0x35fb36d0,0x382c38b7,0x34433521,0x36073736,0x30f932c2,0x331834ce,0x29722e59,0x2bcd308a,0xac89a344,0xae7ea534,0xb1dfb013,0xb42eb1d2,0xb4b3b3a5,0xb6a0b56b,0xb666b58f,0xb872b7c9,
0x36493728,0x385038de,0x347c3565,0x363e3776,0x313e331e,0x335c34fa,0x29be2eb0,0x2c0c30b5,0xacc8a3a8,0xaebda566,0xb22fb04b,0xb455b20a,0xb4f1b406,0xb6dcb59d,0xb6b9b5d8,0xb898b807,
0x3697377e,0x38743904,0x34b635a9,0x367537b6,0x3182337a,0x339f3527,0x2a092f08,0x2c3230e1,0xad07a406,0xaefba598,0xb27fb083,0xb47cb241,0xb530b43a,0xb717b5cf,0xb70cb621,0xb8bdb828,
0x36e437d4,0x3897392a,0x34ee35ed,0x36ab37f5,0x31c633d6,0x33e23554,0x2a542f5f,0x2c57310c,0xad45a439,0xaf3aa5cb,0xb2cfb0bb,0xb4a4b279,0xb56eb46d,0xb752b601,0xb75db669,0xb8e1b84a,
0x37303814,0x38b9394e,0x3527362f,0x36e1381a,0x320a3418,0x34123580,0x2aa02fb6,0x2c7d3137,0xad84a46b,0xaf78a5fd,0xb31eb0f3,0xb4cbb2b0,0xb5acb4a0,0xb78cb632,0xb7adb6b1,0xb905b86b,
0x377c383e,0x38db3972,0x355f3672,0x37173838,0x324e3446,0x343435ac,0x2aeb3007,0x2ca23163,0xadc3a49d,0xafb6a62f,0xb36eb12b,0xb4f1b2e7,0xb5eab4d4,0xb7c6b663,0xb7fdb6f8,0xb928b88b,
0x38fd3996,0x39f33a91,0x374c3857,0x3874393e,0x345535d8,0x355d3730,0x2cc8318e,0x2df532e7,0xaff5a661,0xb0f3a7f3,0xb518b31e,0xb649b46a,0xb800b694,0xb8dbb808,0xb94bb8ab,0xba45b99b,
0x391e39b8,0x3a0f3aad,0x37813875,0x388c3959,0x34763604,0x357d375a,0x2cee31b9,0x2e1a3312,0xb01aa694,0xb112a813,0xb53fb356,0xb66fb485,0xb81cb6c5,0xb8f5b81f,0xb96db8cb,0xba61b9b7,
0x393e39da,0x3a2b3ac7,0x37b63893,0x38a53974,0x3497362f,0x359d3784,0x2d1331e5,0x2e40333d,0xb039a6c6,0xb131a82c,0xb565b38d,0xb694b4a0,0xb838b6f5,0xb90fb836,0xb98eb8ea,0xba7cb9d2,
0x395e39fb,0x3a453ae0,0x37ea38b0,0x38bd398e,0x34b9365b,0x35be37ad,0x2d393210,0x2e653368,0xb058a6f8,0xb150a845,0xb58cb3c3,0xb6b9b4bc,0xb854b725,0xb928b84c,0xb9aeb909,0xba97b9ed,
0x397d3a1b,0x3a5f3af9,0x380f38cd,0x38d539a8,0x34da3686,0x35de37d7,0x2d5e323b,0x2e8b3393,0xb077a72a,0xb16fa85e,0xb5b2b3fa,0xb6deb4d7,0xb870b755,0xb941b863,0xb9ceb927,0xbab0ba07,
0x399b3a3a,0x3a793b10,0x382838ea,0x38ed39c1,0x34fa36b1,0x35fe3800,0x2d843266,0x2eb033bd,0xb096a75d,0xb18ea877,0xb5d8b418,0xb703b4f1,0xb88bb784,0xb95ab879,0xb9edb945,0xbac9ba21,
0x39b93a58,0x3a913b26,0x38423906,0x390439da,0x351b36dc,0x361e3814,0x2daa3291,0x2ed633e8,0xb0b5a78f,0xb1ada890,0xb5feb434,0xb728b50c,0xb8a6b7b3,0xb972b88f,0xba0bb962,0xbae0ba3a,
0x39d73a75,0x3aa93b3c,0x385b3922,0x391b39f2,0x353c3706,0x363e3828,0x2dcf32bc,0x2efb3409,0xb0d4a7c1,0xb1cca8aa,0xb624b44f,0xb74cb527,0xb8c1b7e2,0xb98ab8a5,0xba29b97f,0xbaf7ba52,
0x3ac03b50,0x3b5e3bcb,0x39323a0a,0x39de3ab8,0x365e383c,0x375738d7,0x2f21341f,0x302634c8,0xb1eba8c3,0xb2e1a98c,0xb770b542,0xb846b615,0xb9a2b8bb,0xba51b960,0xbb0dba6a,0xbb9cbb11,
0x3ad73b63,0x3b6e3bd6,0x39493a22,0x39f23acb,0x367d3850,0x377638ea,0x2f463434,0x303934dd,0xb20aa8dc,0xb300a9a5,0xb795b55d,0xb857b62f,0xb9b9b8d0,0xba65b974,0xbb22ba81,0xbba9bb24,
0x3aec3b75,0x3b7d3bdf,0x395f3a39,0x3a063ade,0x369d3864,0x379538fd,0x2f6c3449,0x304b34f1,0xb229a8f5,0xb31ea9be,0xb7b8b577,0xb868b649,0xb9d0b8e5,0xba79b987,0xbb36ba97,0xbbb6bb35,
0x3b013b86,0x3b8c3be7,0x39753a4f,0x3a193af0,0x36bc3878,0x37b3390f,0x2f91345e,0x305e3506,0xb247a90e,0xb33da9d7,0xb7dcb592,0xb879b663,0xb9e7b8fa,0xba8cb99a,0xbb4abaad,0xbbc2bb46,
0x3b153b96,0x3b993bee,0x398a3a65,0x3a2d3b02,0x36dc388b,0x37d13921,0x2fb63473,0x3071351b,0xb266a927,0xb35ca9f0,0xb800b5ac,0xb88ab67d,0xb9fdb90f,0xba9fb9ad,0xbb5cbac3,0xbbccbb56,
0x3b283ba5,0x3ba63bf4,0x39a03a7a,0x3a3f3b13,0x36fb389e,0x37ef3933,0x2fdc3488,0x30833530,0xb285a940,0xb37aaa09,0xb811b5c7,0xb89bb697,0xba12b924,0xbab1b9c0,0xbb6dbad7,0xbbd6bb65,
0x3b3b3bb3,0x3bb23bf9,0x39b53a8f,0x3a523b24,0x371a38b2,0x38073945,0x3001349d,0x30963545,0xb2a4a959,0xb399aa22,0xb823b5e1,0xb8abb6b1,0xba28b938,0xbac3b9d2,0xbb7ebaeb,0xbbdfbb74,
0x3b4d3bc0,0x3bbd3bfc,0x39ca3aa4,0x3a643b34,0x373938c5,0x38153957,0x301334b3,0x30a9355a,0xb2c2a972,0xb3b7aa3b,0xb834b5fb,0xb8bcb6ca,0xba3cb94c,0xbad4b9e4,0xbb8dbaff,0xbbe6bb82,
0x20e921b2,0x31313204,0x1ead2020,0x2f14305e,0x1b121d1b,0x2b822d6b,0xe4817db,0x1ead282c,0x997f94b6,0xa9d7a502,0x9de49c52,0xae40ac96,0xa0849f76,0xb0c8afe8,0xa216a14d,0xb26cb19b,
0x275d2845,0x31cc32b6,0x2502262f,0x2fe830e1,0x214d23a8,0x2c322e0e,0x14b61de4,0x1f7628aa,0xa0209b12,0xaa87a598,0xa46ba27b,0xaefbad20,0xa6c6a598,0xb156b06a,0xa890a7f3,0xb32bb241,
0x2a222b1d,0x32663368,0x282c2927,0x305e3163,0x246b2661,0x2ca22eb0,0x17db20e9,0x20202927,0xa2df9de4,0xab36a62f,0xa75da566,0xafb6adaa,0xa9a5a8aa,0xb1e5b0e1,0xab9baaa0,0xb3e8b2e7,
0x2c4b2cfa,0x3300340c,0x29d72b36,0x30c831e5,0x262f2877,0x2d132f53,0x197f22df,0x208429a5,0xa4cfa020,0xabe6a6c6,0xa927a78f,0xb039ae33,0xabe6aa87,0xb273b156,0xad52aca2,0xb452b38d,
0x2d842e65,0x33993464,0x2b822ca2,0x31313266,0x27f329be,0x2d842ff5,0x1b12246b,0x20e92a22,0xa62fa14d,0xac4ba75d,0xaaa0a8dc,0xb096aebd,0xad13ac32,0xb300b1cc,0xaed6adf5,0xb4b0b418,
0x2ebd2fcf,0x341834bc,0x2c962daa,0x319b32e7,0x28dc2b04,0x2df5304b,0x1c522566,0x214d2aa0,0xa78fa27b,0xaca2a7f3,0xac0ca9f0,0xb0f3af46,0xae33ad20,0xb38db241,0xb02caf46,0xb50cb46a,
0x2ff5309c,0x34643512,0x2d6b2eb0,0x32043368,0x29be2c25,0x2e65309c,0x1d1b2661,0x21b22b1d,0xa877a3a8,0xacfaa845,0xacc8ab04,0xb150afcf,0xaf53ae0e,0xb40cb2b6,0xb0edb04b,0xb568b4bc,
0x30963150,0x34b03568,0x2e402fb6,0x326c33e8,0x2aa02cc8,0x2ed630ed,0x1de4275d,0x22162b9b,0xa927a46b,0xad52a890,0xad84ac0c,0xb1adb02c,0xb039aefb,0xb452b32b,0xb1adb0f3,0xb5c4b50c,
0x34fa35be,0x373e3826,0x32d53434,0x35063627,0x2f46313e,0x316333bd,0x227b2c0c,0x24cf2e01,0xadaaa8dc,0xb032ab36,0xb20ab071,0xb473b291,0xb497b39f,0xb6b4b598,0xb61eb55d,0xb867b7c6,
0x35453612,0x3784384c,0x333d3473,0x35393663,0x2fb6318e,0x319b3406,0x22df2c4b,0x25022e40,0xae01a927,0xb05eab82,0xb266b0b5,0xb4a0b2d5,0xb4ddb409,0xb6f5b5cf,0xb678b5ac,0xb88fb808,
0x358f3666,0x37c93872,0x33a534b3,0x356b36a0,0x301331df,0x31d2342e,0x23442c89,0x25342e7e,0xae59a972,0xb08aabcd,0xb2c2b0f9,0xb4ceb318,0xb521b443,0xb736b607,0xb6d0b5fb,0xb8b7b82c,
0x35d836b9,0x38073898,0x340634f1,0x359d36dc,0x304b322f,0x320a3455,0x23a82cc8,0x25662ebd,0xaeb0a9be,0xb0b5ac0c,0xb31eb13e,0xb4fab35c,0xb565b47c,0xb776b63e,0xb728b649,0xb8deb850,
0x3621370c,0x382838bd,0x343a3530,0x35cf3717,0x3083327f,0x3241347c,0x24062d07,0x25982efb,0xaf08aa09,0xb0e1ac32,0xb37ab182,0xb527b39f,0xb5a9b4b6,0xb7b6b675,0xb77eb697,0xb904b874,
0x3669375d,0x384a38e1,0x346d356e,0x36013752,0x30bb32cf,0x327934a4,0x24392d45,0x25cb2f3a,0xaf5faa54,0xb10cac57,0xb3d6b1c6,0xb554b3e2,0xb5edb4ee,0xb7f5b6ab,0xb7d4b6e4,0xb92ab897,
0x36b137ad,0x386b3905,0x34a035ac,0x3632378c,0x30f3331e,0x32b034cb,0x246b2d84,0x25fd2f78,0xafb6aaa0,0xb137ac7d,0xb418b20a,0xb580b412,0xb62fb527,0xb81ab6e1,0xb814b730,0xb94eb8b9,
0x36f837fd,0x388b3928,0x34d435ea,0x366337c6,0x312b336e,0x32e734f1,0x249d2dc3,0x262f2fb6,0xb007aaeb,0xb163aca2,0xb446b24e,0xb5acb434,0xb672b55f,0xb838b717,0xb83eb77c,0xb972b8db,
0x38ab394b,0x399b3a45,0x36943800,0x380838db,0x331e3518,0x346a3649,0x26612ff5,0x27f330f3,0xb18eacc8,0xb2e7adf5,0xb5d8b455,0xb730b55d,0xb857b74c,0xb93eb874,0xb996b8fd,0xba91b9f3,
0x38cb396d,0x39b73a61,0x36c5381c,0x381f38f5,0x3356353f,0x3485366f,0x2694301a,0x28133112,0xb1b9acee,0xb312ae1a,0xb604b476,0xb75ab57d,0xb875b781,0xb959b88c,0xb9b8b91e,0xbaadba0f,
0x38ea398e,0x39d23a7c,0x36f53838,0x3836390f,0x338d3565,0x34a03694,0x26c63039,0x282c3131,0xb1e5ad13,0xb33dae40,0xb62fb497,0xb784b59d,0xb893b7b6,0xb974b8a5,0xb9dab93e,0xbac7ba2b,
0x390939ae,0x39ed3a97,0x37253854,0x384c3928,0x33c3358c,0x34bc36b9,0x26f83058,0x28453150,0xb210ad39,0xb368ae65,0xb65bb4b9,0xb7adb5be,0xb8b0b7ea,0xb98eb8bd,0xb9fbb95e,0xbae0ba45,
0x392739ce,0x3a073ab0,0x37553870,0x38633941,0x33fa35b2,0x34d736de,0x272a3077,0x285e316f,0xb23bad5e,0xb393ae8b,0xb686b4da,0xb7d7b5de,0xb8cdb80f,0xb9a8b8d5,0xba1bb97d,0xbaf9ba5f,
0x394539ed,0x3a213ac9,0x3784388b,0x3879395a,0x341835d8,0x34f13703,0x275d3096,0x2877318e,0xb266ad84,0xb3bdaeb0,0xb6b1b4fa,0xb800b5fe,0xb8eab828,0xb9c1b8ed,0xba3ab99b,0xbb10ba79,
0x39623a0b,0x3a3a3ae0,0x37b338a6,0x388f3972,0x343435fe,0x350c3728,0x278f30b5,0x289031ad,0xb291adaa,0xb3e8aed6,0xb6dcb51b,0xb814b61e,0xb906b842,0xb9dab904,0xba58b9b9,0xbb26ba91,
0x397f3a29,0x3a523af7,0x37e238c1,0x38a5398a,0x344f3624,0x3527374c,0x27c130d4,0x28aa31cc,0xb2bcadcf,0xb409aefb,0xb706b53c,0xb828b63e,0xb922b85b,0xb9f2b91b,0xba75b9d7,0xbb3cbaa9,
0x3a6a3b0d,0x3b113b9c,0x38bb39a2,0x39603a51,0x35423770,0x36153846,0x28c331eb,0x298c32e1,0xb41faf21,0xb4c8b026,0xb83cb65e,0xb8d7b757,0xba0ab932,0xbab8b9de,0xbb50bac0,0xbbcbbb5e,
0x3a813b22,0x3b243ba9,0x38d039b9,0x39743a65,0x355d3795,0x362f3857,0x28dc320a,0x29a53300,0xb434af46,0xb4ddb039,0xb850b67d,0xb8eab776,0xba22b949,0xbacbb9f2,0xbb63bad7,0xbbd6bb6e,
0x3a973b36,0x3b353bb6,0x38e539d0,0x39873a79,0x357737b8,0x36493868,0x28f53229,0x29be331e,0xb449af6c,0xb4f1b04b,0xb864b69d,0xb8fdb795,0xba39b95f,0xbadeba06,0xbb75baec,0xbbdfbb7d,
0x3aad3b4a,0x3b463bc2,0x38fa39e7,0x399a3a8c,0x359237dc,0x36633879,0x290e3247,0x29d7333d,0xb45eaf91,0xb506b05e,0xb878b6bc,0xb90fb7b3,0xba4fb975,0xbaf0ba19,0xbb86bb01,0xbbe7bb8c,
0x3ac33b5c,0x3b563bcc,0x390f39fd,0x39ad3a9f,0x35ac3800,0x367d388a,0x29273266,0x29f0335c,0xb473afb6,0xb51bb071,0xb88bb6dc,0xb921b7d1,0xba65b98a,0xbb02ba2d,0xbb96bb15,0xbbeebb99,
0x3ad73b6d,0x3b653bd6,0x39243a12,0x39c03ab1,0x35c73811,0x3697389b,0x29403285,0x2a09337a,0xb488afdc,0xb530b083,0xb89eb6fb,0xb933b7ef,0xba7ab9a0,0xbb13ba3f,0xbba5bb28,0xbbf4bba6,
0x3aeb3b7e,0x3b743bdf,0x39383a28,0x39d23ac3,0x35e13823,0x36b138ab,0x295932a4,0x2a223399,0xb49db001,0xb545b096,0xb8b2b71a,0xb945b807,0xba8fb9b5,0xbb24ba52,0xbbb3bb3b,0xbbf9bbb2,
0x3aff3b8d,0x3b823be6,0x394c3a3c,0x39e43ad4,0x35fb3834,0x36ca38bc,0x297232c2,0x2a3b33b7,0xb4b3b013,0xb55ab0a9,0xb8c5b739,0xb957b815,0xbaa4b9ca,0xbb34ba64,0xbbc0bb4d,0xbbfcbbbd,
0x39b839ba,0x3a973ab5,0x39b339b5,0x3a583a78,0x39af39b1,0x3a153a37,0x39aa39ad,0x39cd39f2,0x39a639a8,0x398239a8,0x39a139a4,0x3933395b,0x399d399f,0x38e03909,0x3999399b,0x388938b5,
0xb979b972,0xb865b832,0xb986b980,0xb8c7b896,0xb994b98d,0xb924b8f6,0xb9a1b99b,0xb97db951,0xb9afb9a8,0xb9d2b9a8,0xb9bcb9b5,0xba21b9fa,0xb9c9b9c3,0xba6bba47,0xb9d6b9d0,0xbab0ba8e,
0xb9f4b9fe,0xbac7bae9,0xb9dfb9e9,0xba7ebaa3,0xb9c9b9d4,0xba2dba56,0xb9b3b9be,0xb9d6ba02,0xb99db9a8,0xb979b9a8,0xb986b992,0xb916b948,0xb970b97b,0xb8adb8e2,0xb958b964,0xb840b877,
0x39373927,0x381a37b7,0x39583948,0x38943858,0x39793969,0x390738ce,0x39993989,0x3974393e,0x39b839a8,0x39da39a8,0x39d639c7,0x3a393a0b,0x39f439e5,0x3a903a65,0x3a113a02,0x3ade3ab8,
0x3a2d3a3f,0x3af43b1a,0x3a093a1b,0x3aa23acc,0x39e339f6,0x3a453a74,0x39bc39d0,0x39df3a13,0x399439a8,0x397039a8,0x396b3980,0x38f83935,0x39413956,0x387a38ba,0x3916392b,0x37e83838,
0xb8f3b8d8,0xb79bb705,0xb929b90e,0xb85fb817,0xb95db943,0xb8eab8a6,0xb990b976,0xb96bb92b,0xb9c0b9a8,0xb9e3b9a8,0xb9f0b9d8,0xba50ba1b,0xba1dba07,0xbab3ba83,0xba49ba33,0xbb0abae0,
0xba64ba7c,0xbb1ebb46,0xba31ba4b,0xbac4baf3,0xb9fcba17,0xba5cba92,0xb9c5b9e1,0xb9e7ba23,0xb98bb9a8,0xb966b9a8,0xb94fb96d,0xb8dbb922,0xb911b930,0xb845b891,0xb8d1b8f1,0xb74eb7ee,
0x38ad3887,0x36ff364e,0x38f838d3,0x382a37ac,0x3941391d,0x38cc387c,0x39863964,0x39623918,0x39c939a8,0x39eb39a8,0x3a0939e9,0x3a673a2b,0x3a453a27,0x3ad53aa0,0x3a7e3a62,0x3b323b05,
0x3b453b6e,0x3bbc3bdd,0x3ae53b17,0x3b573b8f,0x3a733aae,0x3ac73b14,0x39f03a33,0x3a113a71,0x395d39a8,0x393739a8,0x38bc390e,0x384038bf,0x380f3867,0x365f3775,0x36af376a,0x341a3540,
0xb65fb593,0xb389b115,0xb7e8b726,0xb625b4f9,0xb8adb852,0xb830b748,0xb958b905,0xb933b8b5,0xb9f4b9a8,0xba15b9a8,0xba7eba3b,0xbad1ba78,0xbaf4babc,0xbb63bb20,0xbb57bb28,0xbbc6bb9b,
0xbb68bb91,0xbbd0bbed,0xbb04bb39,0xbb6fbba6,0xba89bac9,0xbadbbb2b,0xb9f8ba43,0xba19ba7f,0xb954b9a8,0xb92eb9a8,0xb89eb8fb,0xb820b8ab,0xb7b2b83d,0xb5ebb71b,0xb60eb6e3,0xb2deb4b1,
0x35bc34d5,0x32322f0e,0x377a369e,0x35b13469,0x388e3828,0x380f36ee,0x394f38f1,0x392938a0,0x39fc39a8,0x3a1d39a8,0x3a933a4b,0x3ae53a87,0x3b133ad6,0x3b7a3b36,0x3b783b49,0x3bd93bb1,
0x3b873baf,0x3be13bf8,0x3b213b58,0x3b853bbb,0x3a9e3ae3,0x3aee3b41,0x3a003a52,0x3a213a8e,0x394a39a8,0x392439a8,0x387f38e7,0x37fe3896,0x37423812,0x357636c1,0x356a3659,0x31853420,
0xb517b414,0xb0d7abd9,0xb70ab614,0xb53ab3ae,0xb86fb7f9,0xb7ddb693,0xb946b8dd,0xb91fb88c,0xba04b9a8,0xba25b9a8,0xbaa9ba5a,0xbaf7ba95,0xbb2fbaf0,0xbb90bb4b,0xbb96bb67,0xbbe8bbc4,
0xbba3bbc9,0xbbefbbff,0xbb3dbb74,0xbb9abbcd,0xbab3bafc,0xbb01bb55,0xba09ba62,0xba29ba9c,0xb941b9a8,0xb91bb9a8,0xb85fb8d3,0xb7bdb881,0xb6d2b7cd,0xb4ffb665,0xb4c3b5ce,0xb029b31b,
0x346f32a1,0x2ef52248,0x36993587,0x34c33288,0x385037a1,0x379b3637,0x393c38c9,0x39163877,0x3a0d39a8,0x3a2d39a8,0x3abd3a69,0x3b0a3aa3,0x3b4a3b08,0x3ba33b5f,0x3bb03b82,0x3bf43bd5,
0x3bf83c00,0x3bf93bd4,0x3bac3bdc,0x3be43bfe,0x3b133b69,0x3b543bab,0x3a313aaa,0x3a503ae0,0x391139a8,0x38ea39a8,0x377a386d,0x366b3817,0x34873608,0x313b348d,0x2d9731f4,0xad65291b,
0xac3828b6,0x2ec33365,0xb44bb160,0xb0bea57f,0xb759b5da,0xb648b45d,0xb90cb862,0xb8e5b80d,0xba35b9a8,0xba54b9a8,0xbb1bbab1,0xbb5cbae6,0xbbb5bb72,0xbbe9bbb2,0xbbfcbbe3,0xbbf5bc00,
0xbbfebbfc,0xbbefbbbc,0xbbbdbbe9,0xbbeebc00,0xbb24bb7b,0xbb63bbb9,0xba39bab8,0xba58baed,0xb907b9a8,0xb8e0b9a8,0xb737b858,0xb625b802,0xb40eb5ab,0xb042b42c,0xa9b1b0cb,0x30109a48,
0x25e4ad7e,0xb0beb475,0x33a23036,0x2f8ba3db,0x3715357c,0x360233f7,0x3902384d,0x38db37ee,0x3a3d39a8,0x3a5c39a8,0x3b2c3abf,0x3b6a3af3,0x3bc53b84,0x3bf23bc0,0x3bff3bee,0x3be93c00,
0x3c003bf4,0x3be23ba0,0x3bcc3bf3,0x3bf53bff,0x3b353b8c,0x3b713bc6,0x3a413ac6,0x3a603af9,0x38fd39a8,0x38d639a8,0x36f43842,0x35df37d8,0x3328354c,0x2e913396,0x16482f40,0xb16ca852,
0x251b304e,0x32193534,0xb2adae14,0xad972aac,0xb6d2b51d,0xb5bcb334,0xb8f8b838,0xb8d1b7c2,0xba45b9a8,0xba64b9a8,0xbb3dbacc,0xbb78baff,0xbbd3bb95,0xbbf8bbcb,0xbc00bbf7,0xbbdabbfd,
0xbbfebbe6,0xbbd2bb80,0xbbd9bbfa,0xbbfbbbfb,0xbb45bb9d,0xbb7fbbd1,0xba49bad3,0xba67bb05,0xb8f3b9a8,0xb8ccb9a8,0xb6afb82d,0xb599b7ac,0xb232b4ed,0xac9cb2d2,0x294dace7,0x32c62c83,
0xac06b1db,0xb371b5f1,0x31b62b75,0x2b43adb0,0x368d34bd,0x3576326f,0x38ee3822,0x38c73796,0x3a4d39a8,0x3a6b39a8,0x3b4c3ad9,0x3b853b0b,0x3bdf3ba4,0x3bfd3bd6,0x3bfc3bfd,0x3bc83bf8,
0x3bbd3b5a,0x3b473a99,0x3bfe3bf4,0x3bf93bbe,0x3b8b3bdb,0x3bb83bf7,0x3a6f3b11,0x3a8c3b3e,0x38c139a8,0x389939a8,0x35523780,0x343236cc,0x294d320d,0xad332de2,0xb40eaedc,0xb6a4b408,
0x346336aa,0x36f438b0,0xa6ad3004,0x2e2d3451,0xb52fb1aa,0xb40ead1a,0xb8bcb76a,0xb894b6b5,0xba73b9a8,0xba90b9a8,0xbb92bb17,0xbbbdbb43,0xbbffbbe0,0xbbf6bbf9,0xbbb2bbf0,0xbb35bbb4,
0xbba5bb30,0xbb21ba5e,0xbc00bbeb,0xbbf3bbaa,0xbb98bbe4,0xbbc2bbfb,0xba76bb1d,0xba93bb49,0xb8b7b9a8,0xb88eb9a8,0xb50bb753,0xb3d3b69e,0xa17fb147,0x2f27ac51,0x34b73099,0x37423499,
0xb50bb75e,0xb790b900,0x9cb6b12e,0xb010b4e1,0x34e730e4,0x33892b11,0x38b2373d,0x38893687,0x3a7a39a8,0x3a9739a8,0x3b9e3b22,0x3bc63b4e,0x3c003be8,0x3bef3bfd,0x3b983be5,0x3b0d3b9e,
0x3b893b02,0x3af73a1f,0x3c003bdf,0x3beb3b93,0x3ba33bec,0x3bcb3bfe,0x3a7e3b28,0x3a9b3b53,0x38ad39a8,0x388439a8,0x34c33726,0x33403670,0xa51b3080,0xb08d297f,0xb55eb1c3,0xb7ddb529,
0x35b13807,0x3815394d,0x28843257,0x31093570,0xb49fb01d,0xb2f7a7da,0xb8a8b710,0xb87fb659,0xba81b9a8,0xba9eb9a8,0xbba9bb2e,0xbbcfbb58,0xbbffbbef,0xbbe6bbff,0xbb7abbd7,0xbae1bb86,
0xbb6abad0,0xbacbb9dc,0xbbfdbbd0,0xbbe1bb79,0xbbaebbf2,0xbbd3bc00,0xba85bb33,0xbaa2bb5d,0xb8a3b9a8,0xb87ab9a8,0xb47bb6f9,0xb2adb642,0x2a7aaf72,0x3185a4b6,0x360232ea,0x383a35b6,
0xb654b85d,0xb85fb996,0xac38b37d,0xb201b5fd,0x34572eaa,0x32631e48,0x389e36e3,0x3874362b,0x3a8939a8,0x3aa539a8,0x3bb33b39,0x3bd73b62,0x3bfc3bf5,0x3bdc3c00,0x3b593bc7,0x3ab33b6b,
0x39b739b9,0x3a883aa6,0x39b239b4,0x3a483a68,0x39ae39b0,0x3a033a26,0x39a939ab,0x39bb39e0,0x39a539a7,0x396e3995,0x39a039a3,0x391e3947,0x399c399e,0x38ca38f5,0x3997399a,0x3873389f,
0xb97cb975,0xb87eb84c,0xb98ab983,0xb8deb8ae,0xb997b991,0xb93bb90d,0xb9a5b99e,0xb993b967,0xb9b2b9ab,0xb9e6b9bd,0xb9bfb9b9,0xba34ba0e,0xb9ccb9c6,0xba7dba59,0xb9d9b9d3,0xbac0ba9f,
0xb9efb9f9,0xbab6bad9,0xb9d9b9e4,0xba6aba91,0xb9c4b9cf,0xba18ba42,0xb9aeb9b9,0xb9bfb9ec,0xb997b9a3,0xb961b991,0xb981b98c,0xb8fcb92f,0xb96ab975,0xb892b8c8,0xb953b95e,0xb824b85c,
0x3940392f,0x383937f6,0x39613950,0x38b13876,0x39813971,0x392338eb,0x39a03991,0x398e395a,0x39bf39b0,0x39f339c1,0x39de39cf,0x3a4f3a22,0x39fb39ec,0x3aa43a7b,0x3a183a0a,0x3af03acb,
0x3a243a36,0x3ae13b07,0x39ff3a12,0x3a8b3ab7,0x39d939ec,0x3a2c3a5d,0x39b239c6,0x39c439f9,0x398a399e,0x3953398c,0x39613975,0x38d93917,0x3936394b,0x3859389a,0x390b3921,0x37a43816,
0xb901b8e6,0xb7e6b750,0xb936b91c,0xb883b83c,0xb96ab950,0xb90bb8c8,0xb99cb983,0xb98ab94b,0xb9ccb9b4,0xb9ffb9c6,0xb9fbb9e4,0xba6aba36,0xba28ba12,0xbacaba9b,0xba53ba3e,0xbb1dbaf5,
0xba57ba70,0xbb09bb33,0xba24ba3e,0xbaabbadc,0xb9efba0a,0xba40ba77,0xb9b7b9d3,0xb9c8ba05,0xb97cb99a,0xb944b988,0xb940b95e,0xb8b6b8fe,0xb901b921,0xb81eb86b,0xb8c0b8e1,0xb6fcb79e,
0x38c0389a,0x375636a7,0x390b38e6,0x38543800,0x3953392f,0x38f238a4,0x39973975,0x3985393d,0x39d939b9,0x3a0c39ca,0x3a1839f9,0x3a843a4a,0x3a533a36,0x3aed3abb,0x3a8b3a70,0x3b473b1c,
0x3b2e3b5a,0x3ba63bce,0x3aca3afe,0x3b373b74,0x3a533a91,0x3a9d3aef,0x39cc3a12,0x39de3a42,0x39363983,0x38fc3971,0x389238e6,0x37fb3880,0x37c5383c,0x35d136eb,0x3651370d,0x330934ae,
0xb6c3b5fa,0xb460b251,0xb824b788,0xb6b8b590,0xb8d9b880,0xb873b7d5,0xb981b92f,0xb96eb8f5,0xba18b9cf,0xba48b9e0,0xba9dba5d,0xbafabaa6,0xbb0fbad9,0xbb80bb43,0xbb6cbb40,0xbbd8bbb2,
0xbb51bb7d,0xbbbdbbe0,0xbae7bb1f,0xbb4ebb8c,0xba66baa9,0xbaafbb04,0xb9d1ba1e,0xb9e2ba4e,0xb928b97e,0xb8edb96c,0xb86eb8cd,0xb7afb866,0xb74bb80b,0xb54fb684,0xb5a2b679,0xb197b411,
0x362e3549,0x338330de,0x37e6370d,0x3651350e,0x38c0385c,0x38593788,0x397c3921,0x396a38e6,0x3a2439d3,0x3a5339e4,0x3ab63a70,0x3b0f3ab7,0x3b2e3af5,0x3b973b5a,0x3b8d3b61,0x3be83bc7,
0x3b703b9c,0x3bd03bef,0x3b033b3d,0x3b653ba2,0x3a793ac1,0x3ac03b19,0x39d53a2a,0x39e63a59,0x3919397a,0x38de3967,0x384938b4,0x3761384c,0x36cf37b4,0x34cc361d,0x34f035e2,0x302332e4,
0xb596b496,0xb244aecf,0xb783b690,0xb5e8b48a,0xb8a7b836,0xb83eb73a,0xb978b912,0xb965b8d7,0xba30b9d7,0xba5fb9e8,0xbacdba82,0xbb23bac8,0xbb4cbb10,0xbbacbb6f,0xbbaabb7f,0xbbf4bbd8,
0xbb8dbbb7,0xbbe0bbf9,0xbb1dbb5a,0xbb7abbb5,0xba8bbad9,0xbad0bb2d,0xb9d9ba36,0xb9eaba65,0xb90bb975,0xb8cfb963,0xb824b89a,0xb713b831,0xb651b750,0xb447b5b3,0xb43bb549,0xad58b1a4,
0x34fc33c0,0x31032bc0,0x371e3611,0x357e3405,0x388d3811,0x382436eb,0x39733903,0x396138c8,0x3a3c39db,0x3a6a39ec,0x3ae43a94,0x3b373ad9,0x3b673b2a,0x3bbe3b83,0x3bc33b9a,0x3bfc3be7,
0x3bed3bff,0x3bff3bea,0x3b8d3bc7,0x3bcc3bf5,0x3ae13b40,0x3b1d3b83,0x39ef3a70,0x39ff3a9b,0x38c0395e,0x3883394b,0x36c33816,0x357e3750,0x33833549,0x2e84332e,0x28cf3061,0xb0aca5b2,
0xaf7ea376,0x29663166,0xb514b2fd,0xb2bfad71,0xb809b69b,0xb734b555,0xb95cb8b9,0xb949b87b,0xba75b9f1,0xbaa1ba01,0xbb49bae9,0xbb8bbb25,0xbbcfbb96,0xbbf9bbd2,0xbc00bbf2,0xbbe3bbfe,
0xbbf6bc00,0xbbfcbbda,0xbb9fbbd6,0xbbd8bbfb,0xbaf0bb52,0xbb2cbb92,0xb9f3ba7b,0xba03baa6,0xb8b1b95a,0xb873b947,0xb673b7f6,0xb52cb718,0xb276b4de,0xac5eb251,0x2052ae39,0x321f2bf2,
0x2cf4a806,0xad3fb2d8,0x34a831ee,0x31e22a93,0x37db364b,0x36fc3502,0x395738a9,0x3944386b,0x3a8039f5,0x3aab3a05,0x3b5b3af8,0x3b993b33,0x3bdd3ba7,0x3bfd3bdd,0x3bff3bfa,0x3bd13bf9,
0x3bfd3bfd,0x3bf53bc6,0x3baf3be3,0x3be23bff,0x3b003b64,0x3b393ba0,0x39f73a86,0x3a083ab0,0x38a23955,0x38633942,0x362237bf,0x34d836e0,0x31663472,0x286b3172,0xaaf82b5c,0xb390ae84,
0xa8cf2cf4,0x2fc93423,0xb43bb0de,0xb103a484,0xb7a4b5fa,0xb6c3b4ae,0xb953b89a,0xb940b85c,0xba8bb9f9,0xbab6ba0a,0xbb6cbb07,0xbba6bb40,0xbbe8bbb7,0xbc00bbe7,0xbbfabbff,0xbbbabbf1,
0xbc00bbf6,0xbbebbbae,0xbbbebbed,0xbbebbc00,0xbb0fbb74,0xbb47bbad,0xb9fbba91,0xba0cbabb,0xb892b950,0xb854b93d,0xb5d1b788,0xb484b6a7,0xb055b405,0x9248b093,0x2e6ba484,0x347e3086,
0x98b6afe2,0xb128b4d8,0x339c2f97,0x3023a420,0x376c35a8,0x368a345a,0x394e388b,0x393b384c,0x3a9639fd,0x3ac03a0e,0x3b7c3b16,0x3bb33b4d,0x3bf23bc5,0x3c003bef,0x3bf03c00,0x3ba03be5,
0x3bde3b91,0x3b8a3af7,0x3bf23bff,0x3c003be3,0x3b533bb9,0x3b823bdf,0x3a103ac5,0x3a203aec,0x38443939,0x38033925,0x342f366d,0x31b03584,0xa8392f65,0xb15a1d7f,0xb531b1c9,0xb7e0b55b,
0x3269358a,0x35a83819,0xae842a61,0x205231e2,0xb651b405,0xb567b15a,0xb936b83c,0xb923b7f6,0xbacaba12,0xbaf0ba22,0xbbbebb5a,0xbbe3bb88,0xbbfdbbf5,0xbbddbc00,0xbb81bbd6,0xbadfbb7c,
0xbbcebb70,0xbb6dbac6,0xbbf8bbfb,0xbbffbbd6,0xbb60bbc4,0xbb8dbbe7,0xba14bacf,0xba24baf5,0xb834b934,0xb7e6b921,0xb3b4b634,0xb103b549,0x2c44ada3,0x326925b2,0x35e23309,0x384135f4,
0xb3a8b63a,0xb63fb869,0x2cc2ad58,0xa89db2f0,0x3617335f,0x352c30ac,0x3931382c,0x391e37d5,0x3ad43a16,0x3afa3a26,0x3bc93b66,0x3bea3b92,0x3bf93bfa,0x3bcf3bff,0x3b5f3bc5,0x3aad3b5d,
0x3bba3b4c,0x3b4d3a93,0x3bfc3bf6,0x3bfd3bc7,0x3b6c3bce,0x3b973bed,0x3a183ad9,0x3a283afe,0x3824392f,0x37c5391c,0x330935fa,0x3055350e,0xae6b2bc0,0xb377aa61,0xb690b423,0xb890b68a,
0x347236e5,0x36d438b6,0xa9fd2f7e,0x2c1233fd,0xb5dcb2b3,0xb4f0affb,0xb92db81c,0xb919b7b4,0xbaddba1a,0xbb03ba2a,0xbbd3bb72,0xbbf0bb9c,0xbbf2bbfe,0xbbbfbbfc,0xbb38bbaf,0xba77bb3c,
0xbba4bb23,0xbb2aba5b,0xbbffbbee,0xbbfabbb6,0xbb77bbd7,0xbba1bbf3,0xba1cbae2,0xba2cbb07,0xb813b92a,0xb7a4b917,0xb25db5bf,0xaf4cb4d2,0x3048a839,0x34412cf4,0x373a34c0,0x38dc371e,
0xb50eb78e,0xb767b901,0x24e9b0d1,0xadd5b484,0x35a23207,0x34b42e9d,0x3928380b,0x39143793,0x3ae73a1e,0x3b0c3a2e,0x3bdb3b7d,0x3bf53ba6,0x3be93c00,0x3bad3bf7,0x3b0d3b97,0x3a3e3b18,
0xb999b996,0xb889b85d,0xb99db99b,0xb8e0b8b5,0xb9a1b99f,0xb933b909,0xb9a6b9a4,0xb982b95b,0xb9aab9a8,0xb9cdb9a8,0xb9afb9ad,0xba15b9f2,0xb9b3b9b1,0xba58ba37,0xb9b8b9b5,0xba97ba78,
0xb9d6b9dc,0xbab0bad0,0xb9c9b9d0,0xba6bba8e,0xb9bcb9c3,0xba21ba47,0xb9afb9b5,0xb9d2b9fa,0xb9a1b9a8,0xb97db9a8,0xb994b99b,0xb924b951,0xb986b98d,0xb8c7b8f6,0xb979b980,0xb865b896,
0x3958394d,0x38403807,0x39703964,0x38ad3877,0x3986397b,0x391638e2,0x399d3992,0x39793948,0x39b339a8,0x39d639a8,0x39c939be,0x3a2d3a02,0x39df39d4,0x3a7e3a56,0x39f439e9,0x3ac73aa3,
0x3a113a1f,0x3ade3b02,0x39f43a02,0x3a903ab8,0x39d639e5,0x3a393a65,0x39b839c7,0x39da3a0b,0x399939a8,0x397439a8,0x39793989,0x3907393e,0x39583969,0x389438ce,0x39373948,0x381a3858,
0xb916b900,0xb7e8b75e,0xb941b92b,0xb87ab838,0xb96bb956,0xb8f8b8ba,0xb994b980,0xb970b935,0xb9bcb9a8,0xb9dfb9a8,0xb9e3b9d0,0xba45ba13,0xba09b9f6,0xbaa2ba74,0xba2dba1b,0xbaf4bacc,
0xba49ba5e,0xbb0abb30,0xba1dba33,0xbab3bae0,0xb9f0ba07,0xba50ba83,0xb9c0b9d8,0xb9e3ba1b,0xb990b9a8,0xb96bb9a8,0xb95db976,0xb8eab92b,0xb929b943,0xb85fb8a6,0xb8f3b90e,0xb79bb817,
0x38d138b0,0x374e36aa,0x391138f1,0x384537ee,0x394f3930,0x38db3891,0x398b396d,0x39663922,0x39c539a8,0x39e739a8,0x39fc39e1,0x3a5c3a23,0x3a313a17,0x3ac43a92,0x3a643a4b,0x3b1e3af3,
0x3a7e3a99,0x3b323b5a,0x3a453a62,0x3ad53b05,0x3a093a27,0x3a673aa0,0x39c939e9,0x39eb3a2b,0x398639a8,0x396239a8,0x39413964,0x38cc3918,0x38f8391d,0x382a387c,0x38ad38d3,0x36ff37ac,
0xb6afb5f1,0xb41ab1db,0xb80fb76a,0xb65fb540,0xb8bcb867,0xb840b775,0xb95db90e,0xb937b8bf,0xb9f0b9a8,0xba11b9a8,0xba73ba33,0xbac7ba71,0xbae5baae,0xbb57bb14,0xbb45bb17,0xbbbcbb8f,
0xbb57bb80,0xbbc6bbe6,0xbaf4bb28,0xbb63bb9b,0xba7ebabc,0xbad1bb20,0xb9f4ba3b,0xba15ba78,0xb958b9a8,0xb933b9a8,0xb8adb905,0xb830b8b5,0xb7e8b852,0xb625b748,0xb65fb726,0xb389b4f9,
0x360e3534,0x32de304e,0x37b236e3,0x35eb34b1,0x389e383d,0x3820371b,0x395438fb,0x392e38ab,0x39f839a8,0x3a1939a8,0x3a893a43,0x3adb3a7f,0x3b043ac9,0x3b6f3b2b,0x3b683b39,0x3bd03ba6,
0x3b783ba0,0x3bd93bf4,0x3b133b49,0x3b7a3bb1,0x3a933ad6,0x3ae53b36,0x39fc3a4b,0x3a1d3a87,0x394f39a8,0x392939a8,0x388e38f1,0x380f38a0,0x377a3828,0x35b136ee,0x35bc369e,0x32323469,
0xb56ab475,0xb185ad7e,0xb742b659,0xb576b420,0xb87fb812,0xb7feb6c1,0xb94ab8e7,0xb924b896,0xba00b9a8,0xba21b9a8,0xba9eba52,0xbaeeba8e,0xbb21bae3,0xbb85bb41,0xbb87bb58,0xbbe1bbbb,
0xbb96bbbc,0xbbe8bbfc,0xbb2fbb67,0xbb90bbc4,0xbaa9baf0,0xbaf7bb4b,0xba04ba5a,0xba25ba95,0xb946b9a8,0xb91fb9a8,0xb86fb8dd,0xb7ddb88c,0xb70ab7f9,0xb53ab693,0xb517b614,0xb0d7b3ae,
0x34c33365,0x302928b6,0x36d235ce,0x34ff331b,0x385f37cd,0x37bd3665,0x394138d3,0x391b3881,0x3a0939a8,0x3a2939a8,0x3ab33a62,0x3b013a9c,0x3b3d3afc,0x3b9a3b55,0x3ba33b74,0x3bef3bcd,
0x3bb03bd4,0x3bf43c00,0x3b4a3b82,0x3ba33bd5,0x3abd3b08,0x3b0a3b5f,0x3a0d3a69,0x3a2d3aa3,0x393c39a8,0x391639a8,0x385038c9,0x379b3877,0x369937a1,0x34c33637,0x346f3587,0x2ef53288,
0xad972248,0x2d6532a1,0xb487b1f4,0xb13ba91b,0xb77ab608,0xb66bb48d,0xb911b86d,0xb8eab817,0xba31b9a8,0xba50b9a8,0xbb13baaa,0xbb54bae0,0xbbacbb69,0xbbe4bbab,0xbbf8bbdc,0xbbf9bbfe,
0xbbfcbbff,0xbbf5bbc9,0xbbb5bbe3,0xbbe9bc00,0xbb1bbb72,0xbb5cbbb2,0xba35bab1,0xba54bae6,0xb90cb9a8,0xb8e5b9a8,0xb759b862,0xb648b80d,0xb44bb5da,0xb0beb45d,0xac38b160,0x2ec3a57f,
0x29b1abd9,0xb010b414,0x340e30cb,0x30421a48,0x373735ab,0x3625342c,0x39073858,0x38e03802,0x3a3939a8,0x3a5839a8,0x3b243ab8,0x3b633aed,0x3bbd3b7b,0x3bee3bb9,0x3bfe3be9,0x3bef3c00,
0x3bff3bf8,0x3be93baf,0x3bc53bee,0x3bf23c00,0x3b2c3b84,0x3b6a3bc0,0x3a3d3abf,0x3a5c3af3,0x390239a8,0x38db39a8,0x3715384d,0x360237ee,0x33a2357c,0x2f8b33f7,0x25e43036,0xb0bea3db,
0x96482f0e,0x316c34d5,0xb328af40,0xae912852,0xb6f4b54c,0xb5dfb396,0xb8fdb842,0xb8d6b7d8,0xba41b9a8,0xba60b9a8,0xbb35bac6,0xbb71baf9,0xbbccbb8c,0xbbf5bbc6,0xbc00bbf3,0xbbe2bbff,
0xbc00bbed,0xbbdabb91,0xbbd3bbf7,0xbbf8bbfd,0xbb3dbb95,0xbb78bbcb,0xba45bacc,0xba64baff,0xb8f8b9a8,0xb8d1b9a8,0xb6d2b838,0xb5bcb7c2,0xb2adb51d,0xad97b334,0x251bae14,0x32192aac,
0xa94db115,0xb2c6b593,0x32322ce7,0x2c9cac83,0x36af34ed,0x359932d2,0x38f3382d,0x38cc37ac,0x3a4939a8,0x3a6739a8,0x3b453ad3,0x3b7f3b05,0x3bd93b9d,0x3bfb3bd1,0x3bfe3bfa,0x3bd23bfb,
0x3bfc3bdd,0x3bc83b6e,0x3bdf3bfd,0x3bfd3bf8,0x3b4c3ba4,0x3b853bd6,0x3a4d3ad9,0x3a6b3b0b,0x38ee39a8,0x38c739a8,0x368d3822,0x35763796,0x31b634bd,0x2b43326f,0xac062b75,0xb371adb0,
0x340e364e,0x36a43887,0xa94d2edc,0x2d333408,0xb552b20d,0xb432ade2,0xb8c1b780,0xb899b6cc,0xba6fb9a8,0xba8cb9a8,0xbb8bbb11,0xbbb8bb3e,0xbbfebbdb,0xbbf9bbf7,0xbbbdbbf4,0xbb47bbbe,
0xbbb2bb46,0xbb35ba7c,0xbbffbbf0,0xbbf6bbb4,0xbb92bbe0,0xbbbdbbf9,0xba73bb17,0xba90bb43,0xb8bcb9a8,0xb894b9a8,0xb52fb76a,0xb40eb6b5,0xa6adb1aa,0x2e2dad1a,0x34633004,0x36f43451,
0xb4b7b705,0xb742b8d8,0x217fb099,0xaf27b499,0x350b3147,0x33d32c51,0x38b73753,0x388e369e,0x3a7639a8,0x3a9339a8,0x3b983b1d,0x3bc23b49,0x3c003be4,0x3bf33bfb,0x3ba53beb,0x3b213baa,
0x3b983b1a,0x3b0d3a3f,0x3c003be5,0x3bef3b9e,0x3b9e3be8,0x3bc63bfd,0x3a7a3b22,0x3a973b4e,0x38b239a8,0x388939a8,0x34e7373d,0x33893687,0x9cb630e4,0xb0102b11,0xb50bb12e,0xb790b4e1,
0x355e37b7,0x37dd3927,0x251b31c3,0x308d3529,0xb4c3b080,0xb340a97f,0xb8adb726,0xb884b670,0xba7eb9a8,0xba9bb9a8,0xbba3bb28,0xbbcbbb53,0xbc00bbec,0xbbebbbfe,0xbb89bbdf,0xbaf7bb93,
0xbb7abae9,0xbae1b9fe,0xbbffbbd7,0xbbe6bb86,0xbba9bbef,0xbbcfbbff,0xba81bb2e,0xba9ebb58,0xb8a8b9a8,0xb87fb9a8,0xb49fb710,0xb2f7b659,0x2884b01d,0x3109a7da,0x35b13257,0x38153570,
0xb602b832,0xb83ab972,0xaa7ab2ea,0xb185b5b6,0x347b2f72,0x32ad24b6,0x38a336f9,0x387a3642,0x3a8539a8,0x3aa239a8,0x3bae3b33,0x3bd33b5d,0x3bfd3bf2,0x3be13c00,0x3b6a3bd0,0x3acb3b79,
0x3b593ab5,0x3ab339ba,0x3bfc3bc7,0x3bdc3b6b,0x3bb33bf5,0x3bd73c00,0x3a893b39,0x3aa53b62,0x389e39a8,0x387439a8,0x345736e3,0x3263362b,0xac382eaa,0xb2011e48,0xb654b37d,0xb85fb5fd,
0xb99ab997,0xb89fb873,0xb99eb99c,0xb8f5b8ca,0xb9a3b9a0,0xb947b91e,0xb9a7b9a5,0xb995b96e,0xb9abb9a9,0xb9e0b9bb,0xb9b0b9ae,0xba26ba03,0xb9b4b9b2,0xba68ba48,0xb9b9b9b7,0xbaa6ba88,
0xb9d3b9d9,0xba9fbac0,0xb9c6b9cc,0xba59ba7d,0xb9b9b9bf,0xba0eba34,0xb9abb9b2,0xb9bdb9e6,0xb99eb9a5,0xb967b993,0xb991b997,0xb90db93b,0xb983b98a,0xb8aeb8de,0xb975b97c,0xb84cb87e,
0x395e3953,0x385c3824,0x3975396a,0x38c83892,0x398c3981,0x392f38fc,0x39a33997,0x39913961,0x39b939ae,0x39ec39bf,0x39cf39c4,0x3a423a18,0x39e439d9,0x3a913a6a,0x39f939ef,0x3ad93ab6,
0x3a0a3a18,0x3acb3af0,0x39ec39fb,0x3a7b3aa4,0x39cf39de,0x3a223a4f,0x39b039bf,0x39c139f3,0x399139a0,0x395a398e,0x39713981,0x38eb3923,0x39503961,0x387638b1,0x392f3940,0x37f63839,
0xb921b90b,0xb816b7a4,0xb94bb936,0xb89ab859,0xb975b961,0xb917b8d9,0xb99eb98a,0xb98cb953,0xb9c6b9b2,0xb9f9b9c4,0xb9ecb9d9,0xba5dba2c,0xba12b9ff,0xbab7ba8b,0xba36ba24,0xbb07bae1,
0xba3eba53,0xbaf5bb1d,0xba12ba28,0xba9bbaca,0xb9e4b9fb,0xba36ba6a,0xb9b4b9cc,0xb9c6b9ff,0xb983b99c,0xb94bb98a,0xb950b96a,0xb8c8b90b,0xb91cb936,0xb83cb883,0xb8e6b901,0xb750b7e6,
0x38e138c0,0x379e36fc,0x39213901,0x386b381e,0x395e3940,0x38fe38b6,0x399a397c,0x39883944,0x39d339b7,0x3a0539c8,0x3a0a39ef,0x3a773a40,0x3a3e3a24,0x3adc3aab,0x3a703a57,0x3b333b09,
0x3a703a8b,0x3b1c3b47,0x3a363a53,0x3abb3aed,0x39f93a18,0x3a4a3a84,0x39b939d9,0x39ca3a0c,0x39753997,0x393d3985,0x392f3953,0x38a438f2,0x38e6390b,0x38003854,0x389a38c0,0x36a73756,
0xb70db651,0xb4aeb309,0xb83cb7c5,0xb6ebb5d1,0xb8e6b892,0xb880b7fb,0xb983b936,0xb971b8fc,0xba12b9cc,0xba42b9de,0xba91ba53,0xbaefba9d,0xbafebaca,0xbb74bb37,0xbb5abb2e,0xbbcebba6,
0xbb40bb6c,0xbbb2bbd8,0xbad9bb0f,0xbb43bb80,0xba5dba9d,0xbaa6bafa,0xb9cfba18,0xb9e0ba48,0xb92fb981,0xb8f5b96e,0xb880b8d9,0xb7d5b873,0xb788b824,0xb590b6b8,0xb5fab6c3,0xb251b460,
0x367935a2,0x34113197,0x380b374b,0x3684354f,0x38cd386e,0x386637af,0x397e3928,0x396c38ed,0x3a1e39d1,0x3a4e39e2,0x3aa93a66,0x3b043aaf,0x3b1f3ae7,0x3b8c3b4e,0x3b7d3b51,0x3be03bbd,
0x3b613b8d,0x3bc73be8,0x3af53b2e,0x3b5a3b97,0x3a703ab6,0x3ab73b0f,0x39d33a24,0x39e43a53,0x3921397c,0x38e6396a,0x385c38c0,0x37883859,0x370d37e6,0x350e3651,0x3549362e,0x30de3383,
0xb5e2b4f0,0xb2e4b023,0xb7b4b6cf,0xb61db4cc,0xb8b4b849,0xb84cb761,0xb97ab919,0xb967b8de,0xba2ab9d5,0xba59b9e6,0xbac1ba79,0xbb19bac0,0xbb3dbb03,0xbba2bb65,0xbb9cbb70,0xbbefbbd0,
0xbb7fbbaa,0xbbd8bbf4,0xbb10bb4c,0xbb6fbbac,0xba82bacd,0xbac8bb23,0xb9d7ba30,0xb9e8ba5f,0xb912b978,0xb8d7b965,0xb836b8a7,0xb73ab83e,0xb690b783,0xb48ab5e8,0xb496b596,0xaecfb244,
0x3549343b,0x31a42d58,0x37503651,0x35b33447,0x389a3824,0x38313713,0x3975390b,0x396338cf,0x3a3639d9,0x3a6539ea,0x3ad93a8b,0x3b2d3ad0,0x3b5a3b1d,0x3bb53b7a,0x3bb73b8d,0x3bf93be0,
0x3b9a3bc3,0x3be73bfc,0x3b2a3b67,0x3b833bbe,0x3a943ae4,0x3ad93b37,0x39db3a3c,0x39ec3a6a,0x39033973,0x38c83961,0x3811388d,0x36eb3824,0x3611371e,0x3405357e,0x33c034fc,0x2bc03103,
0xb061a8cf,0x25b230ac,0xb549b383,0xb32eae84,0xb816b6c3,0xb750b57e,0xb95eb8c0,0xb94bb883,0xba70b9ef,0xba9bb9ff,0xbb40bae1,0xbb83bb1d,0xbbc7bb8d,0xbbf5bbcc,0xbbffbbed,0xbbeabbff,
0xbbf2bc00,0xbbfebbe3,0xbb96bbcf,0xbbd2bbf9,0xbae9bb49,0xbb25bb8b,0xb9f1ba75,0xba01baa1,0xb8b9b95c,0xb87bb949,0xb69bb809,0xb555b734,0xb2fdb514,0xad71b2bf,0xa376af7e,0x31662966,
0x2e39a052,0xabf2b21f,0x34de3276,0x32512c5e,0x37f63673,0x3718352c,0x395a38b1,0x39473873,0x3a7b39f3,0x3aa63a03,0x3b523af0,0x3b923b2c,0x3bd63b9f,0x3bfb3bd8,0x3c003bf6,0x3bda3bfc,
0x3bfa3bff,0x3bf93bd1,0x3ba73bdd,0x3bdd3bfd,0x3af83b5b,0x3b333b99,0x39f53a80,0x3a053aab,0x38a93957,0x386b3944,0x364b37db,0x350236fc,0x31ee34a8,0x2a9331e2,0xa8062cf4,0xb2d8ad3f,
0xab5c2af8,0x2e843390,0xb472b166,0xb172a86b,0xb7bfb622,0xb6e0b4d8,0xb955b8a2,0xb942b863,0xba86b9f7,0xbab0ba08,0xbb64bb00,0xbba0bb39,0xbbe3bbaf,0xbbffbbe2,0xbbfdbbfd,0xbbc6bbf5,
0xbbffbbfa,0xbbf1bbba,0xbbb7bbe8,0xbbe7bc00,0xbb07bb6c,0xbb40bba6,0xb9f9ba8b,0xba0abab6,0xb89ab953,0xb85cb940,0xb5fab7a4,0xb4aeb6c3,0xb0deb43b,0xa484b103,0x2cf4a8cf,0x34232fc9,
0x2484ae6b,0xb086b47e,0x34053055,0x30931248,0x378835d1,0x36a73484,0x39503892,0x393d3854,0x3a9139fb,0x3abb3a0c,0x3b743b0f,0x3bad3b47,0x3bed3bbe,0x3c003beb,0x3bf63c00,0x3bae3beb,
0x3c003bf0,0x3be53ba0,0x3bc53bf2,0x3bef3c00,0x3b163b7c,0x3b4d3bb3,0x39fd3a96,0x3a0e3ac0,0x388b394e,0x384c393b,0x35a8376c,0x345a368a,0x2f97339c,0xa4203023,0xafe298b6,0xb4d8b128,
0x31c93531,0x355b37e0,0xaf652839,0x9d7f315a,0xb66db42f,0xb584b1b0,0xb939b844,0xb925b803,0xbac5ba10,0xbaecba20,0xbbb9bb53,0xbbdfbb82,0xbbffbbf2,0xbbe3bc00,0xbb91bbde,0xbaf7bb8a,
0xbbd6bb81,0xbb7cbadf,0xbbf5bbfd,0xbc00bbdd,0xbb5abbbe,0xbb88bbe3,0xba12baca,0xba22baf0,0xb83cb936,0xb7f6b923,0xb405b651,0xb15ab567,0x2a61ae84,0x31e22052,0x358a3269,0x381935a8,
0xb309b5e2,0xb5f4b841,0x2da3ac44,0xa5b2b269,0x363433b4,0x35493103,0x39343834,0x392137e6,0x3acf3a14,0x3af53a24,0x3bc43b60,0x3be73b8d,0x3bfb3bf8,0x3bd63bff,0x3b703bce,0x3ac63b6d,
0x3bc53b5f,0x3b5d3aad,0x3bfa3bf9,0x3bff3bcf,0x3b663bc9,0x3b923bea,0x3a163ad4,0x3a263afa,0x382c3931,0x37d5391e,0x335f3617,0x30ac352c,0xad582cc2,0xb2f0a89d,0xb63ab3a8,0xb869b63f,
0x34233690,0x368a3890,0xabc02e6b,0x2a613377,0xb5fab309,0xb50eb055,0xb92fb824,0xb91cb7c5,0xbad9ba18,0xbafeba28,0xbbcebb6c,0xbbedbb97,0xbbf6bbfc,0xbbc7bbfd,0xbb4cbbba,0xba93bb4d,
0xbbafbb38,0xbb3cba77,0xbbfebbf2,0xbbfcbbbf,0xbb72bbd3,0xbb9cbbf0,0xba1abadd,0xba2abb03,0xb81cb92d,0xb7b4b919,0xb2b3b5dc,0xaffbb4f0,0x2f7ea9fd,0x33fd2c12,0x36e53472,0x38b636d4,
0xb4c0b73a,0xb71eb8dc,0x2839b048,0xacf4b441,0x35bf325d,0x34d22f4c,0x392a3813,0x391737a4,0x3ae23a1c,0x3b073a2c,0x3bd73b77,0x3bf33ba1,0x3bee3bff,0x3bb63bfa,0x3b233ba4,0x3a5b3b2a,
0x3b973b0d,0x3b183a3e,0x3c003be9,0x3bf73bad,0x3b7d3bdb,0x3ba63bf5,0x3a1e3ae7,0x3a2e3b0c,0x380b3928,0x37933914,0x320735a2,0x2e9d34b4,0xb0d124e9,0xb484add5,0xb78eb50e,0xb901b767,
0xb97239ba,0x39dc3996,0xb8323ab5,0x3ad0385d,0x3927b9fe,0xba1fb94d,0x37b7bae9,0xbb02b807,0xb8d83a3f,0x3a5e3900,0xb7053b1a,0x3b30375e,0x3887ba7c,0xba99b8b0,0x364ebb46,0xbb5ab6aa,
0xb90039dc,0x3a3f3972,0xad7e3be6,0x3bf83115,0x3807ba99,0xbae9b887,0xabd9bc00,0xbbfca248,0xb5f13b30,0x3b6e3705,0x32a13bed,0x3bd4b04e,0x3365bba0,0xbbc9b4d5,0xb593bbaf,0xbb803475,
0xb88739fe,0x3a99394d,0x35f13bbc,0x3b6eb414,0x3593bb1a,0xbb80b75e,0xb8b0bb02,0xba7c37b7,0xaf0e3bc9,0x3bf43365,0x3a1f39dc,0x3927b972,0xb04ebc00,0xbbed2248,0xbb30b85d,0xb7053ab5,
0xb8073a1f,0x3ae93927,0x39fe3a3f,0x394db900,0x31dbbb80,0xbbddb593,0xbb6eb832,0xb5f13ad0,0x31153c00,0x3be62248,0x3bff32a1,0x28b6bbd4,0xb7b7bb91,0xbb023534,0xbba0304e,0x34d53bed,
0xb7053a3f,0x3b303900,0x3bbc375e,0x3414bb1a,0x2248bbc9,0xbc00b365,0xbbdda8b6,0x31db3bff,0x36aa3bd4,0x3b46b2a1,0x3a7cb64e,0xb8b0bb5a,0xba1fba5e,0xb92738d8,0xb7b739fe,0x3b02394d,
0xb5f13a5e,0x3b6e38d8,0x3bd42bd9,0xb2a1bbfc,0xb115bbf4,0xbbe6af0e,0xb9dc375e,0x39723b1a,0x39273b46,0x3a1fb6aa,0x3475bad0,0xbbafb832,0xbb91b887,0xb5343a99,0x34143c00,0x3bbc2248,
0xb4d53a7c,0x3ba038b0,0x3a3fb593,0xb900bb80,0xb534bc00,0xbb912248,0xb4143ab5,0x3bbc385d,0x3a993a5e,0x3887b8d8,0xb5f1bbfc,0xbb6e2bd9,0xbbffb475,0x28b63baf,0x3ad03a1f,0x3832b927,
0xb3653a99,0x3bc93887,0x36aab996,0xbb46b9ba,0xb7b7bbed,0xbb02304e,0x34d53bfc,0x3ba02bd9,0x3b913927,0x3534ba1f,0xbae9ba3f,0xb8073900,0xbb5a28b6,0x364e3bff,0x3bd43115,0xb2a1bbe6,
0xb1153ab5,0x3be6385d,0xa8b6bb6e,0xbbffb5f1,0xb900bbbc,0xba3f3414,0x3a1f3b30,0x3927b705,0x3bfc375e,0x2bd9bb1a,0xbbedb475,0x304e3baf,0xb9ba3593,0x39963b80,0x3887b832,0xba99bad0,
0xad7e3ad0,0x3bf83832,0xb7b7bbff,0xbb0228b6,0xb9febb6e,0xb94d35f1,0x3bed3887,0x304eba99,0x3bd43414,0xb2a1bbbc,0xb9963534,0x39ba3b91,0xb6aa3900,0x3b463a3f,0xb115bba0,0xbbe6b4d5,
0xa2483ae9,0x3c003807,0xba99bb30,0xb8873705,0xbad0bb02,0xb83237b7,0x3b462d7e,0xb6aabbf8,0x3b1a28b6,0xb75ebbff,0xaf0e3a7c,0x3bf438b0,0xabd93ab5,0x3bfc385d,0xba5ebb5a,0xb8d8364e,
0x2bd93b02,0x3bfc37b7,0xbbedb927,0xb04e3a1f,0xbb6eba7c,0xb5f138b0,0x385db6aa,0xbab5bb46,0x39dcb1db,0xb972bbdd,0x38323c00,0x3ad02248,0x34d53bbc,0x3ba03414,0xbbf4b705,0x2f0e3b30,
0x304e3b1a,0x3bed375e,0xbb91b475,0x35343baf,0xbbd4b9dc,0xb2a13972,0x2248ba7c,0xbc00b8b0,0x3832b64e,0xbad0bb5a,0x3b803a99,0x3593b887,0x39003bfc,0x3a3fabd9,0xb9273414,0x3a1f3bbc,
0x32a13b30,0x3bd43705,0xb996304e,0x39ba3bed,0xbbffb927,0xa8b63a1f,0xb832bbf4,0xbad0af0e,0x3475b8b0,0xbbafba7c,0x3ba03593,0xb4d5bb80,0x3ae93b6e,0x3807b5f1,0x2bd93a99,0x3bfc3887,
0x34753b46,0x3baf36aa,0xb4d53832,0x3ba03ad0,0xbbedb85d,0x304e3ab5,0xbb30bb5a,0xb705364e,0x2248b9fe,0xbc00b94d,0x3887b414,0xba99bbbc,0x3be63a1f,0x3115b927,0x39dc3bf4,0x3972af0e,
0x35933b5a,0x3b80364e,0x31153a99,0x3be63887,0xbba0b705,0x34d53b30,0xbbf4b8d8,0x2f0e3a5e,0xb414bb02,0xbbbcb7b7,0xabd9ba1f,0xbbfcb927,0x3bd43832,0xb2a1bad0,0x3c003972,0xa248b9dc,
0x36aa3b6e,0x3b4635f1,0x38b03bdd,0x3a7c31db,0xbb1ab534,0x375e3b91,0xba3fb04e,0x39003bed,0xb807bbaf,0xbae9b475,0xb94dbbf8,0xb9fead7e,0x3ab53365,0xb85dbbc9,0x39ba28b6,0xb996bbff,
0x37b73b80,0x3b023593,0x3b1a3bc9,0x375eb365,0xba5eb2a1,0x38d83bd4,0xb53435f1,0x3b913b6e,0xb9babbfc,0xb996abd9,0xbbddbae9,0xb1db3807,0x38b0ad7e,0xba7cbbf8,0x28b6b900,0xbbffba3f,
0x385d3b91,0x3ab53534,0x3c003a5e,0x2248b8d8,0xb972ad7e,0x39dc3bf8,0x33653a3f,0x3bc93900,0xbb02bbe6,0xb7b73115,0xbb1ab6aa,0x375e3b46,0x3414b64e,0xbbbcbb5a,0xb94dbbdd,0xb9feb1db,
0x38d83ba0,0x3a5e34d5,0x3b3037b7,0xb705bb02,0xb85d28b6,0x3ab53bff,0x39ba3be6,0x39963115,0xbbc9bb6e,0xb36535f1,0xb6aa31db,0x3b463bdd,0xaf0eb94d,0xbbf4b9fe,0xbbf8bae9,0xad7e3807,
0x394d3baf,0x39fe3475,0x38d82d7e,0xba5ebbf8,0xb64e3115,0x3b5a3be6,0x3bd43b80,0x32a1b593,0xbbffba99,0x28b63887,0x336539ba,0x3bc93996,0xb75ebae9,0xbb1ab807,0xba3fb534,0x39003b91,
0x39ba3bbc,0x39963414,0x31dbb534,0xbbddbb91,0xb3653475,0x3bc93baf,0x3b803927,0xb593ba1f,0xbba0b972,0x34d539dc,0x3a3f3be6,0x39003115,0xb9febbd4,0xb94db2a1,0xb04e35f1,0x3bed3b6e,
0x3a1f3bc9,0x39273365,0xb475b972,0xbbafb9dc,0xabd9364e,0x3bfc3b5a,0x38d831db,0xba5ebbdd,0xbab5b807,0x385d3ae9,0x3c003b30,0x2248b705,0xbb80bbf4,0xb5932f0e,0x38b03b1a,0x3a7c375e,
0x3a7c3bd4,0x38b032a1,0xb972bb5a,0xb9dcb64e,0x2f0e3807,0x3bf43ae9,0x2d7eb534,0xbbf8bb91,0xb94db4d5,0x39fe3ba0,0x3a5e37b7,0xb8d8bb02,0xbc00bb46,0x224836aa,0x3bdd3bc9,0x31dbb365,
0x3ad03bdd,0x383231db,0xbb80bc00,0xb5932248,0x347538d8,0x3baf3a5e,0xb75eb9fe,0xbb1ab94d,0xb705ad7e,0x3b303bf8,0x3414af0e,0xbbbcbbf4,0xbb6eb9dc,0x35f13972,0x3ab538b0,0xb85dba7c,
0x3b1a3be6,0x375e3115,0xbbf4bb46,0x2f0e36aa,0x37053996,0x3b3039ba,0xbae9bbd4,0xb807b2a1,0xb1db304e,0x3bdd3bed,0xb64eb94d,0xbb5ab9fe,0xb9dcb7b7,0x39723b02,0x3365ad7e,0xbbc9bbf8,
0x3b5a3bed,0x364e304e,0xbab5b94d,0x385d39fe,0x38b03a3f,0x3a7c3900,0xbbffbba0,0x28b634d5,0x2d7e3593,0x3bf83b80,0xbb02bbc9,0xb7b7b365,0xb705b1db,0x3b303bdd,0xb807b9ba,0xbae9b996,
0x3b913bf4,0x35342f0e,0xb807b4d5,0x3ae93ba0,0x39ba3ad0,0x39963832,0xba99b972,0x388739dc,0x3593385d,0x3b803ab5,0xbbe6bb6e,0x311535f1,0xad7e304e,0x3bf83bed,0xbbafbbfc,0xb475abd9,
0x3bbc3bf8,0x34142d7e,0xabd92f0e,0x3bfc3bf4,0x3a993b46,0x388736aa,0xb64eb365,0x3b5a3bc9,0x38b039ba,0x3a7c3996,0xb972b85d,0x39dc3ab5,0x34753705,0x3baf3b30,0xbb1aba5e,0x375e38d8,
0x3bdd3bfc,0x31db2bd9,0x364e3807,0x3b5a3ae9,0x3b463ba0,0x36aa34d5,0x31153475,0x3be63baf,0x3a3f3ad0,0x39003832,0xad7e28b6,0x3bf83bff,0x38d83996,0x3a5e39ba,0xb534b2a1,0x3b913bd4,
0x3bf43bff,0x2f0e28b6,0x3a1f3a7c,0x392738b0,0x3bbc3bdd,0x341431db,0x394d39ba,0x39fe3996,0x3b5a3b91,0x364e3534,0x385d38d8,0x3ab53a5e,0x3ad03b1a,0x3832375e,0x36aa37b7,0x3b463b02,
0x3bff3c00,0x28b62248,0x3bc93bd4,0x336532a1,0x3bf83bfc,0x2d7e2bd9,0x3baf3bbc,0x34753414,0x3bed3bf4,0x304e2f0e,0x3b913ba0,0x353434d5,0x3bdd3be6,0x31db3115,0x3b6e3b80,0x35f13593,
0xb5933b6e,0x3b8035f1,0xb1153bdd,0x3be631db,0x34d5bb91,0xbba0b534,0x2f0ebbed,0xbbf4b04e,0xb4143baf,0x3bbc3475,0xabd93bf8,0x3bfc2d7e,0x32a1bbc9,0xbbd4b365,0x2248bbff,0xbc00a8b6,
0x37b73b46,0x3b02b6aa,0x3b1a3832,0x375ebad0,0xb8d8bab5,0xba5e385d,0xbb91b64e,0xb5343b5a,0x39ba39fe,0x3996b94d,0x3bdd3414,0x31dbbbbc,0xba7cb927,0xb8b03a1f,0xbbffaf0e,0xa8b63bf4,
0x3bd43534,0x32a1bb91,0x39bab8d8,0xb996ba5e,0xbbffad7e,0x28b63bf8,0xb8323a3f,0x3ad03900,0x3bafb115,0xb475bbe6,0x34d5bb46,0xbba0b6aa,0xbae9364e,0x38073b5a,0xabd93bdd,0x3bfc31db,
0x3a5eb75e,0xb8d8bb1a,0xb705bbaf,0xbb303475,0xb85d39dc,0x3ab53972,0x39ba3a7c,0x3996b8b0,0x3365bb5a,0xbbc9b64e,0xbb46b887,0xb6aa3a99,0x2f0e3bfc,0x3bf42bd9,0x3bf83414,0x2d7ebbbc,
0x2bd9bbaf,0xbbfcb475,0xbbedad7e,0x304e3bf8,0x35f13be6,0x3b6eb115,0x3ab5b593,0xb85dbb80,0xb9dcba99,0xb9723887,0xb83239ba,0x3ad03996,0x3ba03807,0x34d5bae9,0x2f0ebb91,0xbbf4b534,
0xb9babae9,0xb9963807,0xb1db3b30,0x3bdd3705,0x3bc937b7,0x3365bb02,0xb593bbf8,0xbb802d7e,0xbba028b6,0x34d53bff,0x3a3f3a7c,0x3900b8b0,0x394db85d,0xb9febab5,0xbbedb64e,0xb04e3b5a,
0xbbf8b365,0x2d7e3bc9,0x3b0239dc,0x37b7b972,0x39feb64e,0xb94dbb5a,0xbbedb1db,0x304e3bdd,0xb2a13ae9,0x3bd43807,0x39bab705,0xb996bb30,0xb6aabbf4,0xbb462f0e,0xb1153b1a,0x3be6375e,
0xb8b0385d,0x3a7c3ab5,0x39dcb5f1,0xb972bb6e,0xaf0ebbbc,0xbbf4b414,0xad7e3b30,0x3bf83705,0x39fe3b1a,0x394db75e,0xb8d8bbaf,0xba5e3475,0xbc00b593,0x22483b80,0x3bdd3832,0x31dbbad0,
0x33653bdd,0x3bc931db,0xb6aabc00,0xbb462248,0xbb02ba5e,0xb7b738d8,0x3ba0394d,0x34d5b9fe,0x3b912d7e,0xb534bbf8,0xbae92f0e,0x38073bf4,0xb64e3972,0x3b5a39dc,0x32a1ba7c,0xbbd4b8b0,
0x3b1a3a7c,0x375eb8b0,0xbbf4b593,0x2f0e3b80,0xbb30a248,0x37053c00,0x3807b85d,0xbae9bab5,0x31dbba5e,0xbbddb8d8,0x364e3bfc,0x3b5a2bd9,0x39723baf,0x39dcb475,0xbbc9b927,0xb3653a1f,
0x3b6e304e,0xb5f1bbed,0xb2a139fe,0x3bd4394d,0xb1153a3f,0x3be63900,0xb9dcbba0,0xb97234d5,0xba1fbb80,0xb9273593,0x3baf3365,0xb475bbc9,0x3b9131db,0xb534bbdd,0xb41439ba,0x3bbc3996,
0x3534b900,0xbb91ba3f,0x3ae93b1a,0x3807b75e,0x39ba3bc9,0x3996b365,0xba9928b6,0x38873bff,0xbb80b2a1,0x35933bd4,0xb115bb5a,0xbbe6b64e,0x2d7eba5e,0xbbf8b8d8,0x3baf39fe,0x3475b94d,
0xb807bbf8,0xbae9ad7e,0x39feaf0e,0xb94dbbf4,0x3bdd36aa,0xb1dbbb46,0x35f13bc9,0x3b6e3365,0xb11539ba,0x3be63996,0xbbffb85d,0x28b63ab5,0xbb02bb30,0xb7b73705,0x34d5b8d8,0xbba0ba5e,
0xbbddb9fe,0xb1db394d,0xb64ebbbc,0xbb5ab414,0x36aab75e,0xbb46bb1a,0x3be637b7,0xb115bb02,0x3a3f3bc9,0x3900b365,0xad7e39dc,0x3bf83972,0xba5ea248,0x38d83c00,0xbb91bab5,0xb534385d,
0xba3fa8b6,0x39003bff,0xbbf8b8b0,0x2d7e3a7c,0xb807bbdd,0xbae9b1db,0x2bd9b9ba,0xbbfcb996,0x3b6e3534,0xb5f1bb91,0x3bd43a5e,0x32a1b8d8,0x33653b1a,0x3bc9375e,0xb59337b7,0x3b803b02,
0xa8b63996,0x3bff39ba,0xb365385d,0x3bc93ab5,0xbbf8b9fe,0xad7e394d,0xbbafbae9,0xb4753807,0x304eb900,0xbbedba3f,0x3534b75e,0xbb91bb1a,0x3bdd3a7c,0x31dbb8b0,0x3b6e3b46,0x35f1b6aa,
0x39dc3c00,0x3972a248,0x3ad03bd4,0x3832b2a1,0xb9272bd9,0x3a1f3bfc,0xb7b73414,0x3b023bbc,0xba5ebbf4,0xb8d82f0e,0xbb30bba0,0xb70534d5,0x3887b115,0xba99bbe6,0x364eb593,0xbb5abb80,
0x3bf43972,0xaf0eb9dc,0x3a1f3115,0xb927bbe6,0x34143a99,0x3bbc3887,0x39fe3c00,0x394d2248,0xbb5ab705,0x364e3b30,0xb85d304e,0x3ab53bed,0xb832bba0,0xbad0b4d5,0xbb46bbaf,0xb6aa3475,
0x3887abd9,0xba99bbfc,0xb5f1bae9,0xbb6eb807,0x3b803ba0,0x3593b4d5,0x3a7c3475,0xb8b0bbaf,0xaf0e3832,0x3bf43ad0,0x3a1f3bff,0x392728b6,0xbbedb996,0x304e39ba,0xb70532a1,0x3b303bd4,
0xb414ba1f,0xbbbcb927,0xbbfcba3f,0x2bd93900,0x3a993593,0xb887bb80,0xb64ebad0,0xbb5ab832,0x3a7c3c00,0x38b02248,0x39dc32a1,0xb972bbd4,0xb4753534,0x3baf3b91,0x3b1a3bed,0x375eb04e,
0xbb30bbf4,0xb7052f0e,0xb41434d5,0x3bbc3ba0,0x2248b832,0xbc00bad0,0xbbddb9dc,0x31db3972,0x3b46385d,0xb6aabab5,0xb8b0bb6e,0xba7cb5f1,0x3a1f3bed,0x3927304e,0x37b7abd9,0xbb02bbfc,
0xbb5ab8d8,0x364e3a5e,0x3ab53bfc,0x385d2bd9,0xba7cbbf4,0xb8b0af0e,0xa8b6375e,0x3bff3b1a,0x2d7eb6aa,0xbbf8bb46,0xbb02b832,0x37b73ad0,0x3b303887,0xb705ba99,0xbae9bc00,0xb807a248,
0xb4d53115,0x3ba03be6,0x3a3f36aa,0xb900bb46,0xbb91b996,0x353439ba,0x3bbc3bd4,0x3414b2a1,0xba99bbed,0xb887b04e,0x35f139fe,0x3b6e394d,0xa8b6b7b7,0xbbffbb02,0xb832ad7e,0x3ad03bf8,
0x38323a99,0x3ad03887,0xb593b996,0xbb80b9ba,0xb475304e,0x3baf3bed,0x375e2bd9,0xbb1abbfc,0xbb30b927,0x37053a1f,0x3bbc3a3f,0xb414b900,0xbb6ebbff,0xb5f128b6,0x3ab53be6,0x385d3115,
0x3be63bd4,0x3115b2a1,0xbbffbb5a,0x28b6364e,0x39003ae9,0x3a3f3807,0xba1fbb91,0xb927b534,0xabd934d5,0x3bfc3ba0,0xb04eb7b7,0xbbedbb02,0xb9bab6aa,0x39963b46,0x38873365,0xba99bbc9,
0x3a1f3832,0xb927bad0,0xb47528b6,0x3baf3bff,0x3bfc3b6e,0xabd9b5f1,0xba5eb887,0x38d83a99,0x3ab53bbc,0x385d3414,0xbc00bb91,0x22483534,0x35933900,0x3b803a3f,0xba7cbba0,0xb8b0b4d5,
0x2248b414,0xbc00bbbc,0x3a993b91,0x38873534,0x38323475,0xbad0bbaf,0x36aa3927,0x3b463a1f,0x3b1a39dc,0xb75eb972,0xaf0e3115,0x3bf43be6,0x3bfc3bd4,0x2bd9b2a1,0xb8d8b5f1,0x3a5e3b6e,
0xb9febb02,0xb94db7b7,0x3a5e3927,0xb8d8ba1f,0xb64eb8b0,0xbb5aba7c,0x3bd43b46,0xb2a1b6aa,0x28b6b1db,0xbbffbbdd,0x3bc93c00,0x33652248,0x375e3414,0xbb1abbbc,0x3a3f3b30,0x39003705,
0xbbedbba0,0x304e34d5,0xb534b7b7,0xbb91bb02,0xbbd4bbff,0xb2a1a8b6,0x2248b115,0xbc00bbe6,0xbad0bb6e,0xb832b5f1,0x359331db,0xbb80bbdd,0xb900b9fe,0xba3fb94d,0x39273807,0xba1fbae9,
0xb85db705,0x3ab53b30,0xbc00bbed,0x2248304e,0xb9dcb927,0x39723a1f,0xbbc9bbf4,0xb365af0e,0xbb02ba7c,0x37b738b0,0xbb1abb80,0xb75eb593,0xbbbcbb6e,0x341435f1,0xb9feba99,0xb94db887,
0x34753593,0x3baf3b80,0xb4d5b365,0x3ba03bc9,0x304e32a1,0x3bed3bd4,0xb705b5f1,0x3b303b6e,0xa2482bd9,0x3c003bfc,0xb887b807,0x3a993ae9,0xb115ad7e,0x3be63bf8,0xb972b900,0x39dc3a3f,
0x3b463b5a,0x36aa364e,0x3a7c3a99,0x38b03887,0x3b1a3b30,0x375e3705,0x3a3f3a5e,0x390038d8,0x3ae93b02,0x380737b7,0x39fe3a1f,0x394d3927,0x3ab53ad0,0x385d3832,0x39ba39dc,0x39963972,
0x28b63c00,0x3bffa248,0x33653bd4,0x3bc9b2a1,0xad7ebbfc,0xbbf82bd9,0xb475bbbc,0xbbaf3414,0x304e3bf4,0x3bedaf0e,0x35343ba0,0x3b91b4d5,0xb1dbbbe6,0xbbdd3115,0xb5f1bb80,0xbb6e3593,
0x3bf4a8b6,0xaf0ebbff,0x3a1fb8b0,0xb927ba7c,0xbbbc31db,0x34143bdd,0xb94d3996,0x39fe39ba,0x3b5ab534,0xb64ebb91,0x385dba5e,0xbab5b8d8,0xbad0375e,0x38323b1a,0xb6aa3b02,0x3b4637b7,
0xb1dbbbfc,0xbbdd2bd9,0xbb5ab807,0xb64e3ae9,0x36aa3ba0,0x3b46b4d5,0x3be63475,0x3115bbaf,0xb900bad0,0xba3f3832,0xbbf8a8b6,0x2d7e3bff,0x3a5e3996,0x38d8b9ba,0x3b91b2a1,0xb534bbd4,
0xbbbc2d7e,0x34143bf8,0x2bd93bf4,0x3bfc2f0e,0x3a99b6aa,0xb887bb46,0xb64ebbc9,0xbb5a3365,0xb8b03996,0x3a7c39ba,0x39723ab5,0x39dcb85d,0x3475bb30,0xbbafb705,0xbb1ab8d8,0xb75e3a5e,
0x35343bf4,0x3b91af0e,0x3ae9b4d5,0xb807bba0,0xb996bad0,0xb9ba3832,0xb8873972,0x3a9939dc,0x3b80385d,0x3593bab5,0x3115bb6e,0xbbe6b5f1,0xbbf8b04e,0x2d7e3bed,0x34753bfc,0x3bafabd9,
0x3b5ab04e,0xb64ebbed,0xbab5b9fe,0xb85d394d,0xb8b03900,0x3a7c3a3f,0x3bff34d5,0x28b6bba0,0x2d7ebb80,0xbbf8b593,0xbb023365,0x37b73bc9,0x37053bdd,0x3b30b1db,0x3807b996,0xbae9b9ba,
0xb75ebbe6,0xbb1a3115,0xaf0e3b46,0x3bf436aa,0x3b303996,0x3705b9ba,0xb807bbd4,0xbae932a1,0xbbddb04e,0x31db3bed,0x3b5a394d,0x364eb9fe,0x3972b7b7,0xb9dcbb02,0xbbc9ad7e,0x33653bf8,
0xbad031db,0x38323bdd,0x3b802248,0xb593bc00,0x3475ba5e,0xbbafb8d8,0xb75e394d,0x3b1a39fe,0x37053bf8,0x3b30ad7e,0xb414bbf4,0xbbbcaf0e,0xbb6eb972,0xb5f139dc,0x3ab53a7c,0x385db8b0,
0x38b03bd4,0x3a7cb2a1,0xb9dcbb5a,0xb972364e,0xbbf4b807,0xaf0e3ae9,0x3bf83534,0xad7ebb91,0x39feb4d5,0xb94dbba0,0xb8d837b7,0x3a5e3b02,0xa2483b46,0x3c0036aa,0xb1dbbbc9,0xbbddb365,
0x3a1fb365,0xb927bbc9,0xb47539dc,0x3baf3972,0x2bd93b5a,0x3bfc364e,0xb8d8bbdd,0xba5e31db,0xbab5bae9,0xb85d3807,0x3c003705,0xa248bb30,0x3b802f0e,0xb593bbf4,0xb8b0375e,0x3a7c3b1a,
0xb996bbbc,0xb9ba3414,0x3bdd3534,0xb1dbbb91,0x3bc93475,0xb365bbaf,0xb5933927,0x3b803a1f,0xb4d53972,0x3ba039dc,0xb900bbe6,0xba3f3115,0xb94dbbd4,0xb9fe32a1,0x3bed35f1,0xb04ebb6e,
0xb94d3475,0x39fe3baf,0xb8d8bbf8,0xba5e2d7e,0xb64ebbe6,0xbb5ab115,0x3bd43593,0xb2a1bb80,0x3bff3887,0x28b6ba99,0xb3653996,0x3bc939ba,0xb75e3807,0x3b1a3ae9,0xba3fbb91,0xb9003534,
0x3a5e3ba0,0x38d8b4d5,0xb70537b7,0x3b303b02,0xbab5a8b6,0x385d3bff,0xb996bbe6,0xb9ba3115,0xb365bb6e,0xbbc9b5f1,0x3b4631db,0xb6aabbdd,0x3bf4394d,0x2f0eb9fe,0x2d7e3ae9,0x3bf83807,
0x385db534,0xbab5bb91,0x3c0038d8,0xa248ba5e,0x39723bf8,0x39dcad7e,0xb3653900,0x3bc93a3f,0xbb02b115,0x37b73be6,0xbb1abb46,0xb75e36aa,0xb414bb5a,0xbbbcb64e,0x394db1db,0xb9febbdd,
0xbb02bb80,0xb7b73593,0xb75ebbc9,0xbb1ab365,0x38d8b2a1,0xba5ebbd4,0x3b9135f1,0xb534bb6e,0x39963bfc,0x39baabd9,0x31db3ae9,0x3bdd3807,0xba7cad7e,0x38b03bf8,0xbbffb900,0x28b63a3f,
0xb6aa35f1,0x3b463b6e,0xb8b031db,0x3a7c3bdd,0xbb1abb91,0xb75e3534,0xba3fbbed,0xb900304e,0x3807b475,0xbae9bbaf,0x394dad7e,0xb9febbf8,0x3ab53bc9,0x385db365,0x39ba3bff,0x3996a8b6,
0x3b803b5a,0x3593b64e,0x3be63a99,0x3115b887,0xb4d53705,0x3ba03b30,0xaf0e38d8,0x3bf43a5e,0xbbbcbb02,0xb41437b7,0xbbfcba1f,0xabd93927,0x32a1b832,0xbbd4bad0,0x2248b972,0xbc00b9dc,
0x3475b6aa,0xbbafbb46,0xb4d5bad0,0xbba0b832,0x3bed3ab5,0x304eb85d,0x3b30364e,0xb705bb5a,0x2248394d,0x3c0039fe,0x38873bbc,0x3a993414,0xbbe6b927,0x31153a1f,0xb9dcaf0e,0x39723bf4,
0xbbd4bb30,0xb2a13705,0xb9bab04e,0x39963bed,0xa8b6b927,0xbbffba1f,0xbad0bbf4,0xb8322f0e,0x3baf38b0,0xb475ba7c,0x34d5b593,0xbba0bb80,0x38073b6e,0x3ae935f1,0x3bfc3a99,0x2bd9b887,
0xb04e375e,0x3bed3b1a,0x3b913baf,0x3534b475,0xbbd4b972,0x32a139dc,0x224838b0,0x3c003a7c,0xb832bb5a,0xbad0b64e,0xbb80b887,0x35933a99,0x39002bd9,0xba3fbbfc,0xb927bbbc,0xba1fb414,
0x3bfc3b02,0x2bd9b7b7,0xb04eb927,0xbbedba1f,0x35f13a7c,0x3b6e38b0,0x3ab536aa,0xb85dbb46,0xb972b1db,0x39dc3bdd,0x3ad03c00,0x3832a248,0xbba0bbbc,0xb4d53414,0xaf0e3705,0x3bf43b30,
0xa248b807,0xbc00bae9,0xba99b705,0x38873b30,0x3ad037b7,0xb832bb02,0xbb46bbf8,0xb6aa2d7e,0x3b1a3bff,0x375ea8b6,0xaf0eb8b0,0xbbf4ba7c,0x2bd9385d,0x3bfc3ab5,0x3a5e364e,0xb8d8bb5a,
0xbbf8bad0,0x2d7e3832,0x3b023bff,0x37b728b6,0xb94dbb6e,0xb9feb5f1,0x304e3887,0x3bed3a99,0x32a1b414,0xbbd4bbbc,0xb9bab534,0x39963b91,0x3b463900,0xb6aaba3f,0xbbe6bba0,0xb11534d5,
0x3115385d,0x3be63ab5,0x28b6b5f1,0xbbffbb6e,0xb900b414,0x3a3f3bbc,0x3a1f3705,0xb927bb30,0xbbfcbb1a,0x2bd9375e,0x3bed3baf,0x304eb475,0xb9babb80,0xb996b593,0x38873ad0,0x3a993832,
0x3bc93a99,0xb365b887,0xbb46b996,0x36aa39ba,0x3b023bed,0x37b7304e,0xbba0bbfc,0xb4d52bd9,0x35343927,0x3b913a1f,0xb807ba3f,0xbae9b900,0xb64ea8b6,0x3b5a3bff,0x32a1b115,0xbbd4bbe6,
0xb4d5b8b0,0xbba0ba7c,0x3a3f3b80,0x39003593,0x35342248,0xbb91bc00,0x3414385d,0x3bbc3ab5,0x3a9938d8,0xb887ba5e,0xb5f1abd9,0x3b6e3bfc,0x3bff3baf,0x28b6b475,0xbad0b927,0x38323a1f,
0xbb6eba5e,0x35f138d8,0x32a1abd9,0xbbd4bbfc,0xbbe6bbf4,0xb1152f0e,0x3972375e,0xb9dcbb1a,0xba1fbb46,0xb927b6aa,0x3baf3ad0,0xb475b832,0xb534b887,0xbb91ba99,0x3bbc3c00,0x3414a248,
0x37053900,0x3b303a3f,0xbbbcbb1a,0x3414375e,0x22483365,0x3c003bc9,0xbbddbbff,0xb1db28b6,0xb6aab2a1,0x3b463bd4,0xba7cbb5a,0xb8b0b64e,0xba1fb8d8,0x39273a5e,0xb7b7b94d,0xbb02b9fe,
0x3ae93a1f,0xb807b927,0x394d3a3f,0x39fe3900,0x3bdd3b80,0xb1dbb593,0x35f13832,0x3b6e3ad0,0x3be63c00,0x3115a248,0x28b632a1,0x3bff3bd4,0x3b023b91,0x37b73534,0xb4d5b04e,0x3ba03bed,
0xb887b94d,0xba99b9fe,0x35f13414,0xbb6ebbbc,0xb593b75e,0xbb80bb1a,0x38b037b7,0xba7cbb02,0xaf0eb365,0xbbf4bbc9,0x3a1f3972,0xb927b9dc,0x304e2248,0xbbedbc00,0x3b303ab5,0xb705b85d,
0xba3fb9dc,0x39003972,0xbbf8bbe6,0x2d7e3115,0xbae9ba99,0x38073887,0xbbfcbc00,0xabd92248,0xbb6ebb30,0x35f13705,0xbbd4bbed,0xb2a1b04e,0xbbc9bba0,0x336534d5,0xbb80bbaf,0xb593b475,
0x39723996,0x39dc39ba,0x3832385d,0x3ad03ab5,0x3927394d,0x3a1f39fe,0x37b73807,0x3b023ae9,0x38d83900,0x3a5e3a3f,0x3705375e,0x3b303b1a,0x388738b0,0x3a993a7c,0x364e36aa,0x3b5a3b46,
0x36aa3b5a,0x3b46b64e,0x38b03a99,0x3a7cb887,0xb75ebb30,0xbb1a3705,0xb900ba5e,0xba3f38d8,0x38073b02,0x3ae9b7b7,0x394d3a1f,0x39feb927,0xb85dbad0,0xbab53832,0xb996b9dc,0xb9ba3972,
0x3475bb80,0xbbafb593,0xb4d5bbc9,0xbba03365,0xb04e3bd4,0x3bed32a1,0x37053b6e,0x3b30b5f1,0xa248bbfc,0xbc00abd9,0xb887bae9,0xba993807,0x31153bf8,0x3be6ad7e,0x39723a3f,0x39dcb900,
0xbab53705,0x385d3b30,0xa2483bed,0x3c00304e,0x3972b927,0xb9dcba1f,0xb365bbf4,0xbbc92f0e,0xb7b73a7c,0x3b0238b0,0x375e3b80,0x3b1ab593,0x3414bb6e,0xbbbcb5f1,0xb94dba99,0xb9fe3887,
0x3bed34d5,0x304ebba0,0x3534bb02,0xbb91b7b7,0xbbd428b6,0x32a13bff,0x22483be6,0x3c003115,0x3ad0b5f1,0xb832bb6e,0xb593bbdd,0xbb8031db,0xb900394d,0x3a3f39fe,0x39273ae9,0x3a1fb807,
0xb94dbb02,0xb9fe37b7,0xb8d83927,0x3a5e3a1f,0x3b5a38b0,0x364eba7c,0x32a1bb46,0xbbd4b6aa,0xbbffb1db,0x28b63bdd,0x33653c00,0x3bc9a248,0x3b1ab414,0xb75ebbbc,0xb900bb30,0xba3f3705,
0x22483bbc,0x3c003414,0x3a99b534,0xb887bb91,0xb832bbaf,0xbad03475,0xb6aa3a1f,0x3b463927,0x3b1a3972,0x375eb9dc,0xaf0ebbe6,0xbbf4b115,0xbbfcb2a1,0x2bd93bd4,0x38d83b6e,0x3a5eb5f1,
0x3927b832,0xba1fbad0,0xbbafa8b6,0x34753bff,0xabd93b6e,0x3bfc35f1,0x38d8b887,0xba5eba99,0xb85dbbbc,0xbab53414,0xa2483b91,0x3c003534,0x3b803900,0x3593ba3f,0xb8b0bba0,0xba7c34d5,
0xbbe6b2a1,0x31153bd4,0x3bff364e,0x28b6bb5a,0x3900b807,0xba3fbae9,0xba1f3534,0x39273b91,0x2bd93ba0,0x3bfc34d5,0x304ebb02,0xbbedb7b7,0xb9babb46,0xb99636aa,0x38873bc9,0x3a99b365,
0x3ad03a99,0x3832b887,0xbb80b996,0xb59339ba,0xbbafb04e,0x34753bed,0x3b1aabd9,0xb75ebbfc,0x3705b927,0xbb30ba1f,0xb4143a3f,0x3bbc3900,0x35f13bff,0x3b6e28b6,0xb85dbbe6,0xbab53115,
0xb4d5bbe6,0xbba0b115,0x3a3f3b46,0x3900b6aa,0x3b9139ba,0x3534b996,0xbbbcb2a1,0x34143bd4,0xba99304e,0x38873bed,0x35f1b94d,0xbb6eb9fe,0x28b6bb02,0xbbffb7b7,0x38323bf8,0x3ad0ad7e,
0xb64e38d8,0x3b5a3a5e,0xb85dbbfc,0xbab52bd9,0xb8b0bbf4,0xba7c2f0e,0x3bff375e,0xa8b6bb1a,0x3bf836aa,0xad7ebb46,0xb7b73832,0x3b023ad0,0xb7053887,0x3b303a99,0xb807bc00,0xbae92248,
0x3b302f0e,0xb705bbf4,0x34143ba0,0x3bbc34d5,0x22483ad0,0x3c003832,0xbbddb972,0xb1db39dc,0xbb46bab5,0xb6aa385d,0x38b0b5f1,0xba7cbb6e,0x3a1fb04e,0xb927bbed,0x37b73bfc,0x3b022bd9,
0xbbbcba1f,0xb4143927,0x2bd9ba3f,0xbbfcb900,0x3887b593,0xba99bb80,0x3b5a3ad0,0x364eb832,0x38b03c00,0x3a7ca248,0xb97232a1,0x39dc3bd4,0xbbafb534,0x34753b91,0xb75ebbed,0xbb1ab04e,
0x38873bfc,0x3a992bd9,0xb5f13807,0x3b6e3ae9,0xbb80b4d5,0x35933ba0,0xba7cbbaf,0xb8b03475,0xaf0ebad0,0xbbf4b832,0x3a1fa8b6,0xb927bbff,0x3bed39ba,0x304eb996,0x37053bd4,0x3b3032a1,
0x2f0eb972,0xbbf4b9dc,0x3927b115,0xba1fbbe6,0x3bbc3a99,0x3414b887,0x394d3c00,0x39fea248,0xb64e3705,0x3b5a3b30,0xbab5b04e,0x385d3bed,0xbad0bba0,0xb83234d5,0xb6aabbaf,0xbb46b475,
0xb9dca248,0x39723c00,0xbad0b2a1,0x38323bd4,0xb927bbfc,0xba1fabd9,0xb7b7bbbc,0xbb02b414,0x3a5e2f0e,0xb8d8bbf4,0x3b3034d5,0xb705bba0,0x38873be6,0x3a993115,0x364e3b80,0x3b5a3593,
0x3bff3996,0xa8b6b9ba,0x3bc9385d,0xb365bab5,0x2d7e39fe,0x3bf8394d,0x34753ae9,0x3baf3807,0xbbedb900,0x304e3a3f,0xbb91b75e,0x35343b1a,0xb1dbba7c,0xbbddb8b0,0xb5f1bb46,0xbb6eb6aa,
0xba3fbbff,0xb90028b6,0xbbf8ba7c,0xad7e38b0,0x3807b1db,0xbae9bbdd,0xabd9b996,0xbbfcb9ba,0x3b6e3b91,0x35f1b534,0x3bd438d8,0xb2a1ba5e,0xb365375e,0x3bc93b1a,0x35933b02,0x3b8037b7,
0x31db39fe,0x3bdd394d,0x3b5a3bbc,0x364eb414,0xbb46b75e,0x36aa3b1a,0xb11537b7,0x3be63b02,0xb900bbc9,0xba3fb365,0xbbf8b9dc,0x2d7e3972,0x38d8a248,0xba5ebc00,0xb534bab5,0xbb91b85d,
0x3807ad7e,0xbae9bbf8,0xb9febbf4,0xb94daf0e,0x3bdd3b46,0x31dbb6aa,0x35f1b365,0xbb6ebbc9,0x31153996,0x3be639ba,0x3bff3ab5,0x28b6b85d,0xbb02b705,0x37b73b30,0x34d53a5e,0x3ba038d8,
0xbb91b900,0x35343a3f,0x38073b1a,0x3ae9375e,0xb996bbc9,0xb9bab365,0xb887a8b6,0x3a993bff,0x3593b2a1,0xbb80bbd4,0xbbe6bb5a,0xb115364e,0x3bf83a5e,0xad7eb8d8,0xb475b9fe,0xbbafb94d,
0x3b6e3bed,0x35f1b04e,0xb2a1b94d,0xbbd4b9fe,0x31153900,0x3be63a3f,0x39dc34d5,0xb972bba0,0xba1fb593,0x39273b80,0x3baf3bc9,0x3475b365,0xbb91bbdd,0xb53431db,0x34143996,0x3bbc39ba,
0xb75eba7c,0xbb1ab8b0,0xaf0e3593,0x3bf43b80,0x3705a248,0xbb30bc00,0xbae9b85d,0x38073ab5,0x3bdd3a5e,0xb1dbb8d8,0xbb5abbfc,0xb64e2bd9,0x39dc3baf,0x39723475,0xb365b927,0xbbc9ba1f,
0xb36531db,0x3bc93bdd,0x36aa2248,0xbb46bc00,0xbb02b8d8,0x37b73a5e,0x3ba039fe,0xb4d5b94d,0xbb91bbf8,0xb5342d7e,0x3ae93bf4,0x38072f0e,0xb64eb9dc,0xbb5ab972,0x32a138b0,0x3bd43a7c,
0x3a7c385d,0xb8b0bab5,0xb972b5f1,0x39dc3b6e,0x3bf43bbc,0x2f0eb414,0xbbf8bb30,0x2d7e3705,0x394d3b1a,0x39fe375e,0xba5ebbaf,0xb8d8b475,0xa2483593,0x3c003b80,0xb1dbb832,0xbbddbad0,
0xbbf8bbc9,0xad7e3365,0x3b023972,0xb7b7b9dc,0xb9febb5a,0xb94db64e,0x3bed3bdd,0x304eb1db,0xb2a1b807,0xbbd4bae9,0x39ba3b30,0x39963705,0x36aa2f0e,0xbb46bbf4,0x3115375e,0x3be63b1a,
0x39963ae9,0x39ba3807,0xbbddbb30,0x31db3705,0x336537b7,0x3bc93b02,0xbb80bbf8,0xb593ad7e,0xb4d5a8b6,0x3ba03bff,0xb900ba7c,0xba3fb8b0,0xb9feb85d,0x394d3ab5,0xb04eb64e,0xbbedbb5a,
0xabd9b475,0xbbfcbbaf,0x3bed3bf8,0x304ead7e,0x35f13115,0xbb6ebbe6,0x3ab53b80,0x385d3593,0x39dc3887,0xb972ba99,0x38323996,0x3ad039ba,0x3ba03ae9,0xb4d5b807,0x2f0e3534,0x3bf43b91,
0xb8d8b75e,0x3a5e3b1a,0xbb30bbaf,0xb705b475,0xbab5b9dc,0x385d3972,0xb996ba7c,0xb9bab8b0,0xbbc9bb5a,0x3365364e,0xb6aab887,0xbb46ba99,0xbbf4bbfc,0xaf0e2bd9,0xad7eb414,0xbbf8bbbc,
0x3bd43b91,0xb2a1b534,0x39ba3a5e,0x399638d8,0x3bff3bf8,0x28b6ad7e,0x38323900,0x3ad03a3f,0x3baf3be6,0x34753115,0x34d536aa,0x3ba03b46,0x3ae93b5a,0x3807364e,0x2bd931db,0x3bfc3bdd,
0xbb02bb46,0xb7b7b6aa,0xb75eb832,0xbb1abad0,0xba5ebab5,0xb8d8b85d,0xb534b64e,0xbb91bb5a,0xb996b9fe,0xb9bab94d,0xb1dbb414,0xbbddbbbc,0xb8b0b927,0xba7cba1f,0xa8b6af0e,0xbbffbbf4,
0x359335f1,0x3b803b6e,0x311531db,0x3be63bdd,0x34d53534,0x3ba03b91,0x2f0e304e,0x3bf43bed,0x34143475,0x3bbc3baf,0x2bd92d7e,0x3bfc3bf8,0x32a13365,0x3bd43bc9,0x224828b6,0x3c003bff,
0x40000,0x60002,0xc0008,0xe000a,0x380034,0x3a0036,0x40003c,0x42003e,0x6c0068,0x6e006a,0x740070,0x760072,0xa0009c,0xa2009e,0xa800a4,0xaa00a6,
0xd400d0,0xd600d2,0xdc00d8,0xde00da,0x1080104,0x10a0106,0x110010c,0x112010e,0x13c0138,0x13e013a,0x1440140,0x1460142,0x170016c,0x172016e,0x1780174,0x17a0176,
0x1a401a0,0x1a601a2,0x1ac01a8,0x1ae01aa,0x1d801d4,0x1da01d6,0x1e001dc,0x1e201de,0x20c0208,0x20e020a,0x2140210,0x2160212,0x240023c,0x242023e,0x2480244,0x24a0246,
0x2740270,0x2760272,0x27c0278,0x27e027a,0x2a802a4,0x2aa02a6,0x2b002ac,0x2b202ae,0x2dc02d8,0x2de02da,0x2e402e0,0x2e602e2,0x310030c,0x312030e,0x3180314,0x31a0316,
0x3440340,0x3460342,0x34c0348,0x34e034a,0x3780374,0x37a0376,0x380037c,0x382037e,0x3ac03a8,0x3ae03aa,0x3b403b0,0x3b603b2,0x3e003dc,0x3e203de,0x3e803e4,0x3ea03e6,
0x4140410,0x4160412,0x41c0418,0x41e041a,0x4480444,0x44a0446,0x450044c,0x452044e,0x47c0478,0x47e047a,0x4840480,0x4860482,0x4b004ac,0x4b204ae,0x4b804b4,0x4ba04b6,
0x4e404e0,0x4e604e2,0x4ec04e8,0x4ee04ea,0x5180514,0x51a0516,0x520051c,0x522051e,0x54c0548,0x54e054a,0x5540550,0x5560552,0x580057c,0x582057e,0x5880584,0x58a0586,
0x5b405b0,0x5b605b2,0x5bc05b8,0x5be05ba,0x5e805e4,0x5ea05e6,0x5f005ec,0x5f205ee,0x61c0618,0x61e061a,0x6240620,0x6260622,0x650064c,0x652064e,0x6580654,0x65a0656,
0x140010,0x160012,0x120010,0x440012,0x480044,0x4a0046,0x460044,0x780046,0x7c0078,0x7e007a,0x7a0078,0xac007a,0xb000ac,0xb200ae,0xae00ac,0xe000ae,
0xe400e0,0xe600e2,0xe200e0,0x11400e2,0x1180114,0x11a0116,0x1160114,0x1480116,0x14c0148,0x14e014a,0x14a0148,0x17c014a,0x180017c,0x182017e,0x17e017c,0x1b0017e,
0x1b401b0,0x1b601b2,0x1b201b0,0x1e401b2,0x1e801e4,0x1ea01e6,0x1e601e4,0x21801e6,0x21c0218,0x21e021a,0x21a0218,0x24c021a,0x250024c,0x252024e,0x24e024c,0x280024e,
0x2840280,0x2860282,0x2820280,0x2b40282,0x2b802b4,0x2ba02b6,0x2b602b4,0x2e802b6,0x2ec02e8,0x2ee02ea,0x2ea02e8,0x31c02ea,0x320031c,0x322031e,0x31e031c,0x350031e,
0x3540350,0x3560352,0x3520350,0x3840352,0x3880384,0x38a0386,0x3860384,0x3b80386,0x3bc03b8,0x3be03ba,0x3ba03b8,0x3ec03ba,0x3f003ec,0x3f203ee,0x3ee03ec,0x42003ee,
0x4240420,0x4260422,0x4220420,0x4540422,0x4580454,0x45a0456,0x4560454,0x4880456,0x48c0488,0x48e048a,0x48a0488,0x4bc048a,0x4c004bc,0x4c204be,0x4be04bc,0x4f004be,
0x4f404f0,0x4f604f2,0x4f204f0,0x52404f2,0x5280524,0x52a0526,0x5260524,0x5580526,0x55c0558,0x55e055a,0x55a0558,0x58c055a,0x590058c,0x592058e,0x58e058c,0x5c0058e,
0x5c405c0,0x5c605c2,0x5c205c0,0x5f405c2,0x5f805f4,0x5fa05f6,0x5f605f4,0x62805f6,0x62c0628,0x62e062a,0x62a0628,0x65c062a,0x660065c,0x662065e,0x65e065c,0x18065e,
0x180018,0x4c001a,0x1a0018,0x4c001a,0x4c004c,0x80004e,0x4e004c,0x80004e,0x800080,0xb40082,0x820080,0xb40082,0xb400b4,0xe800b6,0xb600b4,0xe800b6,
0xe800e8,0x11c00ea,0xea00e8,0x11c00ea,0x11c011c,0x150011e,0x11e011c,0x150011e,0x1500150,0x1840152,0x1520150,0x1840152,0x1840184,0x1b80186,0x1860184,0x1b80186,
0x1b801b8,0x1ec01ba,0x1ba01b8,0x1ec01ba,0x1ec01ec,0x22001ee,0x1ee01ec,0x22001ee,0x2200220,0x2540222,0x2220220,0x2540222,0x2540254,0x2880256,0x2560254,0x2880256,
0x2880288,0x2bc028a,0x28a0288,0x2bc028a,0x2bc02bc,0x2f002be,0x2be02bc,0x2f002be,0x2f002f0,0x32402f2,0x2f202f0,0x32402f2,0x3240324,0x3580326,0x3260324,0x3580326,
0x3580358,0x38c035a,0x35a0358,0x38c035a,0x38c038c,0x3c0038e,0x38e038c,0x3c0038e,0x3c003c0,0x3f403c2,0x3c203c0,0x3f403c2,0x3f403f4,0x42803f6,0x3f603f4,0x42803f6,
0x4280428,0x45c042a,0x42a0428,0x45c042a,0x45c045c,0x490045e,0x45e045c,0x490045e,0x4900490,0x4c40492,0x4920490,0x4c40492,0x4c404c4,0x4f804c6,0x4c604c4,0x4f804c6,
0x4f804f8,0x52c04fa,0x4fa04f8,0x52c04fa,0x52c052c,0x560052e,0x52e052c,0x560052e,0x5600560,0x5940562,0x5620560,0x5940562,0x5940594,0x5c80596,0x5960594,0x5c80596,
0x5c805c8,0x5fc05ca,0x5ca05c8,0x5fc05ca,0x5fc05fc,0x63005fe,0x5fe05fc,0x63005fe,0x6300630,0x6640632,0x6320630,0x6640632,0x6640664,0x1c0666,0x6660664,0x1c0666,
0x1c001c,0x50001e,0x1e001c,0x50001e,0x500050,0x840052,0x520050,0x840052,0x840084,0xb80086,0x860084,0xb80086,0xb800b8,0xec00ba,0xba00b8,0xec00ba,
0xec00ec,0x12000ee,0xee00ec,0x12000ee,0x1200120,0x1540122,0x1220120,0x1540122,0x1540154,0x1880156,0x1560154,0x1880156,0x1880188,0x1bc018a,0x18a0188,0x1bc018a,
0x1bc01bc,0x1f001be,0x1be01bc,0x1f001be,0x1f001f0,0x22401f2,0x1f201f0,0x22401f2,0x2240224,0x2580226,0x2260224,0x2580226,0x2580258,0x28c025a,0x25a0258,0x28c025a,
0x28c028c,0x2c0028e,0x28e028c,0x2c0028e,0x2c002c0,0x2f402c2,0x2c202c0,0x2f402c2,0x2f402f4,0x32802f6,0x2f602f4,0x32802f6,0x3280328,0x35c032a,0x32a0328,0x35c032a,
0x35c035c,0x390035e,0x35e035c,0x390035e,0x3900390,0x3c40392,0x3920390,0x3c40392,0x3c403c4,0x3f803c6,0x3c603c4,0x3f803c6,0x3f803f8,0x42c03fa,0x3fa03f8,0x42c03fa,
0x42c042c,0x460042e,0x42e042c,0x460042e,0x4600460,0x4940462,0x4620460,0x4940462,0x4940494,0x4c80496,0x4960494,0x4c80496,0x4c804c8,0x4fc04ca,0x4ca04c8,0x4fc04ca,
0x4fc04fc,0x53004fe,0x4fe04fc,0x53004fe,0x5300530,0x5640532,0x5320530,0x5640532,0x5640564,0x5980566,0x5660564,0x5980566,0x5980598,0x5cc059a,0x59a0598,0x5cc059a,
0x5cc05cc,0x60005ce,0x5ce05cc,0x60005ce,0x6000600,0x6340602,0x6020600,0x6340602,0x6340634,0x6680636,0x6360634,0x6680636,0x6680668,0x20066a,0x66a0668,0x20066a,
0x5d605d6,0x60a05d6,0x5d605d6,0x60a060a,0x60a060a,0x63e063e,0x60a060a,0x63e063e,0x63e063e,0x672063e,0x63e063e,0x6720672,0x6720672,0x280028,0x6720672,0x280028,
0x5060506,0x53a0506,0x5060506,0x53a053a,0x53a053a,0x56e056e,0x53a053a,0x56e056e,0x56e056e,0x5a2056e,0x56e056e,0x5a205a2,0x5a205a2,0x5d605d6,0x5a205a2,0x5d605d6,
0x4360436,0x46a0436,0x4360436,0x46a046a,0x46a046a,0x49e049e,0x46a046a,0x49e049e,0x49e049e,0x4d2049e,0x49e049e,0x4d204d2,0x4d204d2,0x5060506,0x4d204d2,0x5060506,
0x3660366,0x39a0366,0x3660366,0x39a039a,0x39a039a,0x3ce03ce,0x39a039a,0x3ce03ce,0x3ce03ce,0x40203ce,0x3ce03ce,0x4020402,0x4020402,0x4360436,0x4020402,0x4360436,
0x2960296,0x2ca0296,0x2960296,0x2ca02ca,0x2ca02ca,0x2fe02fe,0x2ca02ca,0x2fe02fe,0x2fe02fe,0x33202fe,0x2fe02fe,0x3320332,0x3320332,0x3660366,0x3320332,0x3660366,
0x1c601c6,0x1fa01c6,0x1c601c6,0x1fa01fa,0x1fa01fa,0x22e022e,0x1fa01fa,0x22e022e,0x22e022e,0x262022e,0x22e022e,0x2620262,0x2620262,0x2960296,0x2620262,0x2960296,
0xf600f6,0x12a00f6,0xf600f6,0x12a012a,0x12a012a,0x15e015e,0x12a012a,0x15e015e,0x15e015e,0x192015e,0x15e015e,0x1920192,0x1920192,0x1c601c6,0x1920192,0x1c601c6,
0x260026,0x5a0026,0x260026,0x5a005a,0x5a005a,0x8e008e,0x5a005a,0x8e008e,0x8e008e,0xc2008e,0x8e008e,0xc200c2,0xc200c2,0xf600f6,0xc200c2,0xf600f6,
0x5d405d4,0x60805d4,0x5d405d4,0x6080608,0x6080608,0x63c063c,0x6080608,0x63c063c,0x63c063c,0x670063c,0x63c063c,0x6700670,0x6700670,0x260026,0x6700670,0x260026,
0x5040504,0x5380504,0x5040504,0x5380538,0x5380538,0x56c056c,0x5380538,0x56c056c,0x56c056c,0x5a0056c,0x56c056c,0x5a005a0,0x5a005a0,0x5d405d4,0x5a005a0,0x5d405d4,
0x4340434,0x4680434,0x4340434,0x4680468,0x4680468,0x49c049c,0x4680468,0x49c049c,0x49c049c,0x4d0049c,0x49c049c,0x4d004d0,0x4d004d0,0x5040504,0x4d004d0,0x5040504,
0x3640364,0x3980364,0x3640364,0x3980398,0x3980398,0x3cc03cc,0x3980398,0x3cc03cc,0x3cc03cc,0x40003cc,0x3cc03cc,0x4000400,0x4000400,0x4340434,0x4000400,0x4340434,
0x2940294,0x2c80294,0x2940294,0x2c802c8,0x2c802c8,0x2fc02fc,0x2c802c8,0x2fc02fc,0x2fc02fc,0x33002fc,0x2fc02fc,0x3300330,0x3300330,0x3640364,0x3300330,0x3640364,
0x1c401c4,0x1f801c4,0x1c401c4,0x1f801f8,0x1f801f8,0x22c022c,0x1f801f8,0x22c022c,0x22c022c,0x260022c,0x22c022c,0x2600260,0x2600260,0x2940294,0x2600260,0x2940294,
0xf400f4,0x12800f4,0xf400f4,0x1280128,0x1280128,0x15c015c,0x1280128,0x15c015c,0x15c015c,0x190015c,0x15c015c,0x1900190,0x1900190,0x1c401c4,0x1900190,0x1c401c4,
0x240024,0x580024,0x240024,0x580058,0x580058,0x8c008c,0x580058,0x8c008c,0x8c008c,0xc0008c,0x8c008c,0xc000c0,0xc000c0,0xf400f4,0xc000c0,0xf400f4,
0x5d205d2,0x60605d2,0x5d205d2,0x6060606,0x6060606,0x63a063a,0x6060606,0x63a063a,0x63a063a,0x66e063a,0x63a063a,0x66e066e,0x66e066e,0x240024,0x66e066e,0x240024,
0x5020502,0x5360502,0x5020502,0x5360536,0x5360536,0x56a056a,0x5360536,0x56a056a,0x56a056a,0x59e056a,0x56a056a,0x59e059e,0x59e059e,0x5d205d2,0x59e059e,0x5d205d2,
0x4320432,0x4660432,0x4320432,0x4660466,0x4660466,0x49a049a,0x4660466,0x49a049a,0x49a049a,0x4ce049a,0x49a049a,0x4ce04ce,0x4ce04ce,0x5020502,0x4ce04ce,0x5020502,
0x3620362,0x3960362,0x3620362,0x3960396,0x3960396,0x3ca03ca,0x3960396,0x3ca03ca,0x3ca03ca,0x3fe03ca,0x3ca03ca,0x3fe03fe,0x3fe03fe,0x4320432,0x3fe03fe,0x4320432,
0x2920292,0x2c60292,0x2920292,0x2c602c6,0x2c602c6,0x2fa02fa,0x2c602c6,0x2fa02fa,0x2fa02fa,0x32e02fa,0x2fa02fa,0x32e032e,0x32e032e,0x3620362,0x32e032e,0x3620362,
0x1c201c2,0x1f601c2,0x1c201c2,0x1f601f6,0x1f601f6,0x22a022a,0x1f601f6,0x22a022a,0x22a022a,0x25e022a,0x22a022a,0x25e025e,0x25e025e,0x2920292,0x25e025e,0x2920292,
0xf200f2,0x12600f2,0xf200f2,0x1260126,0x1260126,0x15a015a,0x1260126,0x15a015a,0x15a015a,0x18e015a,0x15a015a,0x18e018e,0x18e018e,0x1c201c2,0x18e018e,0x1c201c2,
0x220022,0x560022,0x220022,0x560056,0x560056,0x8a008a,0x560056,0x8a008a,0x8a008a,0xbe008a,0x8a008a,0xbe00be,0xbe00be,0xf200f2,0xbe00be,0xf200f2,
0x5d005d0,0x60405d0,0x5d005d0,0x6040604,0x6040604,0x6380638,0x6040604,0x6380638,0x6380638,0x66c0638,0x6380638,0x66c066c,0x66c066c,0x220022,0x66c066c,0x220022,
0x5000500,0x5340500,0x5000500,0x5340534,0x5340534,0x5680568,0x5340534,0x5680568,0x5680568,0x59c0568,0x5680568,0x59c059c,0x59c059c,0x5d005d0,0x59c059c,0x5d005d0,
0x4300430,0x4640430,0x4300430,0x4640464,0x4640464,0x4980498,0x4640464,0x4980498,0x4980498,0x4cc0498,0x4980498,0x4cc04cc,0x4cc04cc,0x5000500,0x4cc04cc,0x5000500,
0x3600360,0x3940360,0x3600360,0x3940394,0x3940394,0x3c803c8,0x3940394,0x3c803c8,0x3c803c8,0x3fc03c8,0x3c803c8,0x3fc03fc,0x3fc03fc,0x4300430,0x3fc03fc,0x4300430,
0x2900290,0x2c40290,0x2900290,0x2c402c4,0x2c402c4,0x2f802f8,0x2c402c4,0x2f802f8,0x2f802f8,0x32c02f8,0x2f802f8,0x32c032c,0x32c032c,0x3600360,0x32c032c,0x3600360,
0x1c001c0,0x1f401c0,0x1c001c0,0x1f401f4,0x1f401f4,0x2280228,0x1f401f4,0x2280228,0x2280228,0x25c0228,0x2280228,0x25c025c,0x25c025c,0x2900290,0x25c025c,0x2900290,
0xf000f0,0x12400f0,0xf000f0,0x1240124,0x1240124,0x1580158,0x1240124,0x1580158,0x1580158,0x18c0158,0x1580158,0x18c018c,0x18c018c,0x1c001c0,0x18c018c,0x1c001c0,
0x200020,0x540020,0x200020,0x540054,0x540054,0x880088,0x540054,0x880088,0x880088,0xbc0088,0x880088,0xbc00bc,0xbc00bc,0xf000f0,0xbc00bc,0xf000f0,
0x30003000,0x30003000,0x30003000,0x30003000,0x30003000,0x30003000,0x30003000,0x30003000,0x0,0x0,0x0,0x0,0x0,0x0,0x0,0x0,
0x30003000,0x30003000,0x30003000,0x30003000,0x30003000,0x30003000,0x30003000,0x30003000,0x0,0x0,0x0,0x0,0x0,0x0,0x0,0x0,
0x2a1f2da8,0xaf64ada8,0xaa1fada8,0x2f642da8,0x2f643000,0xaa1f0000,0xaf64b000,0x2a1f8000,0x2f642da8,0x2a1f2da8,0xaf64ada8,0xaa1fada8,0x2a1f0000,0x2f643000,0xaa1f0000,0xaf64b000,
0x263e2c72,0xafd9aea7,0xa63eac72,0x2fd92ea7,0x2ea72fd9,0xac72a63e,0xaea7afd9,0x2c72263e,0x2fd92ea7,0x263e2c72,0xafd9aea7,0xa63eac72,0x2c72263e,0x2ea72fd9,0xac72a63e,0xaea7afd9,
0x2da80000,0xada80000,0x2da88000,0xada80000,0x2da83000,0xada8b000,0x2da83000,0xada8b000,0x2da83000,0xada8b000,0x2da83000,0xada8b000,0xada80000,0x2da88000,0xada80000,0x2da88000,
0x2f642a1f,0xaf64aa1f,0x2f642a1f,0xaf64aa1f,0x2a1f2f64,0xaa1faf64,0x2a1f2f64,0xaa1faf64,0x2a1f2f64,0xaa1faf64,0x2a1f2f64,0xaa1faf64,0xaf64aa1f,0x2f642a1f,0xaf64aa1f,0x2f642a1f,
0xaa1f2da8,0x2f642da8,0x2a1fada8,0xaf64ada8,0x2f640000,0xaa1fb000,0xaf640000,0x2a1f3000,0xaf64ada8,0xaa1f2da8,0x2f642da8,0x2a1fada8,0x2a1f3000,0x2f648000,0xaa1fb000,0xaf640000,
0xaea7263e,0x2c722fd9,0x2ea7a63e,0xac72afd9,0x2fd92c72,0x263eaea7,0xafd9ac72,0xa63e2ea7,0xac72afd9,0xaea7263e,0x2c722fd9,0x2ea7a63e,0xa63e2ea7,0x2fd92c72,0x263eaea7,0xafd9ac72,
0xada82da8,0xada82da8,0xada82da8,0xada82da8,0x2da8ada8,0x2da8ada8,0x2da8ada8,0x2da8ada8,0x2da82da8,0x2da82da8,0x2da82da8,0x2da82da8,0xada8ada8,0xada8ada8,0xada8ada8,0xada8ada8,
0x3000,0x3000,0x3000,0x80003000,0x8000b000,0x8000b000,0x8000b000,0x8000b000,0x30000000,0x30008000,0x30008000,0x30008000,0xb0000000,0xb0000000,0xb0000000,0xb0000000,
0x2ea7263e,0xac722fd9,0xaea7a63e,0x2c72afd9,0xafd92c72,0xa63eaea7,0x2fd9ac72,0x263e2ea7,0x2c72afd9,0x2ea7263e,0xac722fd9,0xaea7a63e,0x263e2ea7,0xafd92c72,0xa63eaea7,0x2fd9ac72,
0x2f64ada8,0x2a1f2da8,0xaf642da8,0xaa1fada8,0xaa1f3000,0xaf640000,0x2a1fb000,0x2f648000,0xaa1fada8,0x2f64ada8,0x2a1f2da8,0xaf642da8,0x2f640000,0xaa1f3000,0xaf640000,0x2a1fb000,
0xaa1f2f64,0x2a1faf64,0xaa1f2f64,0x2a1faf64,0x2f64aa1f,0xaf642a1f,0x2f64aa1f,0xaf642a1f,0xaf642a1f,0x2f64aa1f,0xaf642a1f,0x2f64aa1f,0xaa1f2f64,0x2a1faf64,0xaa1f2f64,0x2a1faf64,
0x2da80000,0xada80000,0x2da88000,0xada80000,0x2da8b000,0xada83000,0x2da8b000,0xada83000,0xada83000,0x2da8b000,0xada83000,0x2da8b000,0x2da88000,0xada80000,0x2da88000,0xada88000,
0xa63e2c72,0x2fd9aea7,0x263eac72,0xafd92ea7,0xaea72fd9,0x2c72a63e,0x2ea7afd9,0xac72263e,0xafd92ea7,0xa63e2c72,0x2fd9aea7,0x263eac72,0xac72263e,0xaea72fd9,0x2c72a63e,0x2ea7afd9,
0x2f64ada8,0x2a1fada8,0xaf642da8,0xaa1f2da8,0x2a1f0000,0x2f64b000,0xaa1f0000,0xaf643000,0xaa1f2da8,0x2f64ada8,0x2a1fada8,0xaf642da8,0xaf643000,0x2a1f8000,0x2f64b000,0xaa1f8000,
0xb0003000,0xb0003000,0xb0003000,0xb0003000,0xb0003000,0xb0003000,0xb0003000,0xb0003000,0x0,0x8000,0x8000,0x80008000,0x8000,0x8000,0x8000,0x8000,
0x80000000,0x80000000,0x80008000,0x80008000,0x80000000,0x80008000,0x80008000,0x80008000,0xb0003000,0xb0003000,0xb0003000,0xb0003000,0xb0003000,0xb0003000,0xb0003000,0xb0003000,
0xaa1f2da8,0x2f64ada8,0x2a1fada8,0xaf642da8,0xaf643000,0x2a1f0000,0x2f64b000,0xaa1f8000,0xaf642da8,0xaa1f2da8,0x2f64ada8,0x2a1fada8,0xaa1f0000,0xaf643000,0x2a1f0000,0x2f64b000,
0x2fd9aea7,0x263eac72,0xafd92ea7,0xa63e2c72,0x2c72a63e,0x2ea7afd9,0xac72263e,0xaea72fd9,0xa63e2c72,0x2fd9aea7,0x263eac72,0xafd92ea7,0xaea72fd9,0x2c72a63e,0x2ea7afd9,0xac72263e,
0xada80000,0x2da80000,0xada88000,0x2da80000,0xada83000,0x2da8b000,0xada83000,0x2da8b000,0xada83000,0x2da8b000,0xada83000,0x2da8b000,0x2da80000,0xada88000,0x2da88000,0xada88000,
0xaa1f2f64,0x2a1faf64,0xaa1f2f64,0x2a1faf64,0x2f64aa1f,0xaf642a1f,0x2f64aa1f,0xaf642a1f,0x2f64aa1f,0xaf642a1f,0x2f64aa1f,0xaf642a1f,0x2a1faf64,0xaa1f2f64,0x2a1faf64,0xaa1f2f64,
0x2a1f2da8,0xaf642da8,0xaa1fada8,0x2f64ada8,0xaf640000,0x2a1fb000,0x2f640000,0xaa1f3000,0x2f64ada8,0x2a1f2da8,0xaf642da8,0xaa1fada8,0xaa1f3000,0xaf648000,0x2a1fb000,0x2f640000,
0x2c72afd9,0x2ea7263e,0xac722fd9,0xaea7a63e,0x263e2ea7,0xafd92c72,0xa63eaea7,0x2fd9ac72,0xaea7a63e,0x2c72afd9,0x2ea7263e,0xac722fd9,0x2fd9ac72,0x263e2ea7,0xafd92c72,0xa63eaea7,
0x2da8ada8,0x2da8ada8,0x2da8ada8,0x2da8ada8,0xada82da8,0xada82da8,0xada82da8,0xada82da8,0x2da82da8,0x2da82da8,0x2da82da8,0x2da82da8,0xada8ada8,0xada8ada8,0xada8ada8,0xada8ada8,
0x80003000,0x80003000,0x80003000,0x3000,0xb000,0x8000b000,0xb000,0xb000,0xb0000000,0xb0008000,0xb0008000,0xb0008000,0x30000000,0x30000000,0x30000000,0x30008000,
0x2c722fd9,0x2ea7a63e,0xac72afd9,0xaea7263e,0x263eaea7,0xafd9ac72,0xa63e2ea7,0x2fd92c72,0xaea7263e,0x2c722fd9,0x2ea7a63e,0xac72afd9,0x2fd92c72,0x263eaea7,0xafd9ac72,0xa63e2ea7,
0xaf64ada8,0xaa1f2da8,0x2f642da8,0x2a1fada8,0x2a1f3000,0x2f648000,0xaa1fb000,0xaf648000,0x2a1fada8,0xaf64ada8,0xaa1f2da8,0x2f642da8,0xaf640000,0x2a1f3000,0x2f648000,0xaa1fb000,
0x2f642a1f,0xaf64aa1f,0x2f642a1f,0xaf64aa1f,0x2a1f2f64,0xaa1faf64,0x2a1f2f64,0xaa1faf64,0xaa1faf64,0x2a1f2f64,0xaa1faf64,0x2a1f2f64,0x2f642a1f,0xaf64aa1f,0x2f642a1f,0xaf64aa1f,
0xada80000,0x2da80000,0xada88000,0x2da88000,0xada8b000,0x2da83000,0xada8b000,0x2da83000,0x2da83000,0xada8b000,0x2da83000,0xada8b000,0xada88000,0x2da88000,0xada88000,0x2da80000,
0x2fd92ea7,0x263e2c72,0xafd9aea7,0xa63eac72,0x2c72263e,0x2ea72fd9,0xac72a63e,0xaea7afd9,0xa63eac72,0x2fd92ea7,0x263e2c72,0xafd9aea7,0xaea7afd9,0x2c72263e,0x2ea72fd9,0xac72a63e,
0xaf64ada8,0xaa1fada8,0x2f642da8,0x2a1f2da8,0xaa1f0000,0xaf64b000,0x2a1f0000,0x2f643000,0x2a1f2da8,0xaf64ada8,0xaa1fada8,0x2f642da8,0x2f643000,0xaa1f8000,0xaf64b000,0x2a1f0000,
0x80008000,0x80008000,0x80008000,0x80008000,0x80008000,0x80008000,0x80008000,0x80008000,0x30003000,0x30003000,0x30003000,0x30003000,0x30003000,0x30003000,0x30003000,0x30003000,
0x80008000,0x80008000,0x80008000,0x80008000,0x80008000,0x80008000,0x80008000,0x80008000,0x30003000,0x30003000,0x30003000,0x30003000,0x30003000,0x30003000,0x30003000,0x30003000,
0xaf64ada8,0xaa1fada8,0x2f642da8,0x2a1f2da8,0xaa1f8000,0xaf64b000,0x2a1f8000,0x2f643000,0x2a1f2da8,0xaf64ada8,0xaa1fada8,0x2f642da8,0x2f643000,0xaa1f0000,0xaf64b000,0x2a1f8000,
0xafd9aea7,0xa63eac72,0x2fd92ea7,0x263e2c72,0xac72a63e,0xaea7afd9,0x2c72263e,0x2ea72fd9,0x263e2c72,0xafd9aea7,0xa63eac72,0x2fd92ea7,0x2ea72fd9,0xac72a63e,0xaea7afd9,0x2c72263e,
0x2da83000,0xada8b000,0x2da83000,0xada8b000,0xada80000,0x2da88000,0xada80000,0x2da88000,0xada88000,0x2da88000,0xada80000,0x2da88000,0xada8b000,0x2da83000,0xada8b000,0x2da83000,
0x2a1f2f64,0xaa1faf64,0x2a1f2f64,0xaa1faf64,0xaf64aa1f,0x2f642a1f,0xaf64aa1f,0x2f642a1f,0xaf64aa1f,0x2f642a1f,0xaf64aa1f,0x2f642a1f,0xaa1faf64,0x2a1f2f64,0xaa1faf64,0x2a1f2f64,
0xaf64ada8,0xaa1f2da8,0x2f642da8,0x2a1fada8,0x2a1f3000,0x2f648000,0xaa1fb000,0xaf640000,0x2a1fada8,0xaf64ada8,0xaa1f2da8,0x2f642da8,0xaf648000,0x2a1f3000,0x2f648000,0xaa1fb000,
0xac72afd9,0xaea7263e,0x2c722fd9,0x2ea7a63e,0xa63e2ea7,0x2fd92c72,0x263eaea7,0xafd9ac72,0x2ea7a63e,0xac72afd9,0xaea7263e,0x2c722fd9,0xafd9ac72,0xa63e2ea7,0x2fd92c72,0x263eaea7,
0xada8ada8,0xada8ada8,0xada8ada8,0xada8ada8,0x2da82da8,0x2da82da8,0x2da82da8,0x2da82da8,0xada82da8,0xada82da8,0xada82da8,0xada82da8,0x2da8ada8,0x2da8ada8,0x2da8ada8,0x2da8ada8,
0xb0008000,0xb0000000,0xb0000000,0xb0000000,0x30008000,0x30008000,0x30008000,0x30008000,0x3000,0x3000,0x3000,0x80003000,0x8000b000,0x8000b000,0x8000b000,0x8000b000,
0xac722fd9,0xaea7a63e,0x2c72afd9,0x2ea7263e,0xa63eaea7,0x2fd9ac72,0x263e2ea7,0xafd92c72,0x2ea7263e,0xac722fd9,0xaea7a63e,0x2c72afd9,0xafd92c72,0xa63eaea7,0x2fd9ac72,0x263e2ea7,
0x2a1f2da8,0xaf642da8,0xaa1fada8,0x2f64ada8,0xaf648000,0x2a1fb000,0x2f648000,0xaa1f3000,0x2f64ada8,0x2a1f2da8,0xaf642da8,0xaa1fada8,0xaa1f3000,0xaf640000,0x2a1fb000,0x2f648000,
0xaf642a1f,0x2f64aa1f,0xaf642a1f,0x2f64aa1f,0xaa1f2f64,0x2a1faf64,0xaa1f2f64,0x2a1faf64,0x2a1faf64,0xaa1f2f64,0x2a1faf64,0xaa1f2f64,0xaf642a1f,0x2f64aa1f,0xaf642a1f,0x2f64aa1f,
0xada83000,0x2da8b000,0xada83000,0x2da8b000,0x2da88000,0xada80000,0x2da88000,0xada88000,0xada88000,0x2da88000,0xada80000,0x2da88000,0xada83000,0x2da8b000,0xada83000,0x2da8b000,
0xafd92ea7,0xa63e2c72,0x2fd9aea7,0x263eac72,0xac72263e,0xaea72fd9,0x2c72a63e,0x2ea7afd9,0x263eac72,0xafd92ea7,0xa63e2c72,0x2fd9aea7,0x2ea7afd9,0xac72263e,0xaea72fd9,0x2c72a63e,
0xaa1f2da8,0x2f64ada8,0x2a1fada8,0xaf642da8,0xaf643000,0x2a1f8000,0x2f64b000,0xaa1f8000,0xaf642da8,0xaa1f2da8,0x2f64ada8,0x2a1fada8,0xaa1f8000,0xaf643000,0x2a1f8000,0x2f64b000,
0x80008000,0x80000000,0x80000000,0x0,0x80000000,0x80000000,0x80000000,0x80000000,0xb0003000,0xb0003000,0xb0003000,0xb0003000,0xb0003000,0xb0003000,0xb0003000,0xb0003000,
0x3000b000,0x3000b000,0x3000b000,0x3000b000,0x3000b000,0x3000b000,0x3000b000,0x3000b000,0x80000000,0x80000000,0x80008000,0x80008000,0x80000000,0x80008000,0x80008000,0x80008000,
0x2f64ada8,0x2a1fada8,0xaf642da8,0xaa1f2da8,0x2a1f8000,0x2f64b000,0xaa1f8000,0xaf643000,0xaa1f2da8,0x2f64ada8,0x2a1fada8,0xaf642da8,0xaf643000,0x2a1f0000,0x2f64b000,0xaa1f8000,
0x263eac72,0xafd92ea7,0xa63e2c72,0x2fd9aea7,0x2ea7afd9,0xac72263e,0xaea72fd9,0x2c72a63e,0x2fd9aea7,0x263eac72,0xafd92ea7,0xa63e2c72,0x2c72a63e,0x2ea7afd9,0xac72263e,0xaea72fd9,
0xada83000,0x2da8b000,0xada83000,0x2da8b000,0x2da80000,0xada88000,0x2da88000,0xada88000,0x2da88000,0xada88000,0x2da80000,0xada88000,0x2da8b000,0xada83000,0x2da8b000,0xada83000,
0x2f64aa1f,0xaf642a1f,0x2f64aa1f,0xaf642a1f,0x2a1faf64,0xaa1f2f64,0x2a1faf64,0xaa1f2f64,0x2a1faf64,0xaa1f2f64,0x2a1faf64,0xaa1f2f64,0xaf642a1f,0x2f64aa1f,0xaf642a1f,0x2f64aa1f,
0x2f64ada8,0x2a1f2da8,0xaf642da8,0xaa1fada8,0xaa1f3000,0xaf648000,0x2a1fb000,0x2f640000,0xaa1fada8,0x2f64ada8,0x2a1f2da8,0xaf642da8,0x2f648000,0xaa1f3000,0xaf648000,0x2a1fb000,
0xaea7a63e,0x2c72afd9,0x2ea7263e,0xac722fd9,0x2fd9ac72,0x263e2ea7,0xafd92c72,0xa63eaea7,0xac722fd9,0xaea7a63e,0x2c72afd9,0x2ea7263e,0xa63eaea7,0x2fd9ac72,0x263e2ea7,0xafd92c72,
0xada8ada8,0xada8ada8,0xada8ada8,0xada8ada8,0x2da82da8,0x2da82da8,0x2da82da8,0x2da82da8,0x2da8ada8,0x2da8ada8,0x2da8ada8,0x2da8ada8,0xada82da8,0xada82da8,0xada82da8,0xada82da8,
0x30008000,0x30000000,0x30000000,0x30000000,0xb0008000,0xb0008000,0xb0008000,0xb0000000,0x80003000,0x80003000,0x80003000,0x3000,0xb000,0x8000b000,0xb000,0xb000,
0x2ea7a63e,0xac72afd9,0xaea7263e,0x2c722fd9,0xafd9ac72,0xa63e2ea7,0x2fd92c72,0x263eaea7,0x2c722fd9,0x2ea7a63e,0xac72afd9,0xaea7263e,0x263eaea7,0xafd9ac72,0xa63e2ea7,0x2fd92c72,
0xaa1f2da8,0x2f642da8,0x2a1fada8,0xaf64ada8,0x2f648000,0xaa1fb000,0xaf640000,0x2a1f3000,0xaf64ada8,0xaa1f2da8,0x2f642da8,0x2a1fada8,0x2a1f3000,0x2f648000,0xaa1fb000,0xaf648000,
0xaa1faf64,0x2a1f2f64,0xaa1faf64,0x2a1f2f64,0x2f642a1f,0xaf64aa1f,0x2f642a1f,0xaf64aa1f,0xaf64aa1f,0x2f642a1f,0xaf64aa1f,0x2f642a1f,0xaa1faf64,0x2a1f2f64,0xaa1faf64,0x2a1f2f64,
0x2da83000,0xada8b000,0x2da83000,0xada8b000,0xada88000,0x2da88000,0xada88000,0x2da80000,0x2da88000,0xada88000,0x2da80000,0xada80000,0x2da83000,0xada8b000,0x2da83000,0xada8b000,
0xa63eac72,0x2fd92ea7,0x263e2c72,0xafd9aea7,0xaea7afd9,0x2c72263e,0x2ea72fd9,0xac72a63e,0xafd9aea7,0xa63eac72,0x2fd92ea7,0x263e2c72,0xac72a63e,0xaea7afd9,0x2c72263e,0x2ea72fd9,
0x2a1f2da8,0xaf64ada8,0xaa1fada8,0x2f642da8,0x2f643000,0xaa1f8000,0xaf64b000,0x2a1f0000,0x2f642da8,0x2a1f2da8,0xaf64ada8,0xaa1fada8,0x2a1f8000,0x2f643000,0xaa1f8000,0xaf64b000,
0x3c003c00,0x3c003c00,0x3c003c00,0x3c003c00,0x3c003c00,0x3c003c00,0x3c003c00,0x3c003c00,0x80008000,0x80008000,0x80008000,0x80008000,0x80008000,0x80008000,0x80008000,0x80008000,
0x3bd93c00,0x3aa73b64,0x387239a8,0x323e361f,0xb23e0000,0xb872b61f,0xbaa7b9a8,0xbbd9bb64,0xb23e8000,0xb872b61f,0xbaa7b9a8,0xbbd9bb64,0xbbd9bc00,0xbaa7bb64,0xb872b9a8,0xb23eb61f,
0xbb64bc00,0xb61fb9a8,0x361f8000,0x3b6439a8,0x3b643c00,0x361f39a8,0xb61f0000,0xbb64b9a8,0x361f8000,0x3b6439a8,0x3b643c00,0x361f39a8,0xb61f8000,0xbb64b9a8,0xbb64bc00,0xb61fb9a8,
0x38728000,0x3bd93b64,0x323e39a8,0xbaa7b61f,0x3aa73c00,0xb23e361f,0xbbd9b9a8,0xb872bb64,0x3aa73c00,0xb23e361f,0xbbd9b9a8,0xb872bb64,0xb8728000,0xbbd9bb64,0xb23eb9a8,0x3aa7361f,
0xbc008000,0x3c008000,0xbc000000,0x3c008000,0xbc000000,0x3c008000,0xbc000000,0x3c008000,0x3c00,0x8000bc00,0x3c00,0x8000bc00,0x3c00,0x8000bc00,0x80003c00,0x8000bc00,
0xbbd98000,0x3aa7361f,0xb872b9a8,0x323e3b64,0x323ebc00,0xb8723b64,0x3aa7b9a8,0xbbd9361f,0xb23e3c00,0x3872bb64,0xbaa739a8,0x3bd9b61f,0xbbd90000,0x3aa7361f,0xb872b9a8,0x323e3b64,
0x3b648000,0xb61fb9a8,0xb61f3c00,0x3b64b9a8,0xbb648000,0x361f39a8,0x361fbc00,0xbb6439a8,0x361fbc00,0xbb6439a8,0x3b648000,0xb61fb9a8,0xb61f3c00,0x3b64b9a8,0xbb640000,0x361f39a8,
0xb8723c00,0x3bd9b61f,0xb23eb9a8,0xbaa73b64,0xbaa78000,0xb23e3b64,0x3bd9b9a8,0xb872b61f,0x3aa78000,0x323ebb64,0xbbd939a8,0x3872361f,0xb8723c00,0x3bd9b61f,0xb23eb9a8,0xbaa73b64,
0xbbd93c00,0xbaa73b64,0xb87239a8,0xb23e361f,0x323e8000,0x3872b61f,0x3aa7b9a8,0x3bd9bb64,0x323e8000,0x3872b61f,0x3aa7b9a8,0x3bd9bb64,0x3bd9bc00,0x3aa7bb64,0x3872b9a8,0x323eb61f,
0xbc003c00,0xbc003c00,0xbc003c00,0xbc003c00,0xbc003c00,0xbc003c00,0xbc003c00,0xbc003c00,0x80008000,0x80000000,0x80000000,0x80000000,0x80000000,0x80000000,0x0,0x80000000,
0xb8728000,0xbbd93b64,0xb23e39a8,0x3aa7b61f,0xbaa73c00,0x323e361f,0x3bd9b9a8,0x3872bb64,0xbaa73c00,0x323e361f,0x3bd9b9a8,0x3872bb64,0x38728000,0x3bd9bb64,0x323eb9a8,0xbaa7361f,
0x3b64bc00,0x361fb9a8,0xb61f8000,0xbb6439a8,0xbb643c00,0xb61f39a8,0x361f0000,0x3b64b9a8,0xb61f8000,0xbb6439a8,0xbb643c00,0xb61f39a8,0x361f8000,0x3b64b9a8,0x3b64bc00,0x361fb9a8,
0x3bd98000,0xbaa7361f,0x3872b9a8,0xb23e3b64,0xb23ebc00,0x38723b64,0xbaa7b9a8,0x3bd9361f,0x323e3c00,0xb872bb64,0x3aa739a8,0xbbd9b61f,0x3bd98000,0xbaa7361f,0x3872b9a8,0xb23e3b64,
0x3c008000,0xbc008000,0x3c000000,0xbc008000,0x3c000000,0xbc008000,0x3c000000,0xbc000000,0x80003c00,0xbc00,0x80003c00,0x8000bc00,0x80003c00,0xbc00,0x80003c00,0xbc00,
0x38723c00,0xbbd9b61f,0x323eb9a8,0x3aa73b64,0x3aa78000,0x323e3b64,0xbbd9b9a8,0x3872b61f,0xbaa78000,0xb23ebb64,0x3bd939a8,0xb872361f,0x38723c00,0xbbd9b61f,0x323eb9a8,0x3aa73b64,
0xbb640000,0x361fb9a8,0x361f3c00,0xbb64b9a8,0x3b648000,0xb61f39a8,0xb61fbc00,0x3b6439a8,0xb61fbc00,0x3b6439a8,0xbb640000,0x361fb9a8,0x361f3c00,0xbb64b9a8,0x3b648000,0xb61f39a8,
0x39a83c00,0xb9a80000,0xb9a8bc00,0x39a88000,0x39a83c00,0xb9a80000,0xb9a8bc00,0x39a88000,0xb9a88000,0xb9a8bc00,0x39a88000,0x39a83c00,0xb9a80000,0xb9a8bc00,0x39a88000,0x39a83c00,
0x38723c00,0xbbd9b61f,0x323eb9a8,0x3aa73b64,0xbaa70000,0xb23ebb64,0x3bd939a8,0xb872361f,0xbaa78000,0xb23ebb64,0x3bd939a8,0xb872361f,0xb872bc00,0x3bd9361f,0xb23e39a8,0xbaa7bb64,
0xb61fbc00,0x3b6439a8,0xbb640000,0x361fb9a8,0x361f3c00,0xbb64b9a8,0x3b648000,0xb61f39a8,0x3b648000,0xb61f39a8,0xb61fbc00,0x3b6439a8,0xbb648000,0x361fb9a8,0x361f3c00,0xbb64b9a8,
0x3bd98000,0xbaa7361f,0x3872b9a8,0xb23e3b64,0x323e3c00,0xb872bb64,0x3aa739a8,0xbbd9b61f,0x323e3c00,0xb872bb64,0x3aa739a8,0xbbd9b61f,0xbbd98000,0x3aa7b61f,0xb87239a8,0x323ebb64,
0xb9a88000,0xb9a83c00,0x39a88000,0x39a8bc00,0xb9a80000,0xb9a83c00,0x39a88000,0x39a8bc00,0xb9a83c00,0x39a88000,0x39a8bc00,0xb9a80000,0xb9a83c00,0x39a88000,0x39a8bc00,0xb9a88000,
0xb8728000,0xbbd93b64,0xb23e39a8,0x3aa7b61f,0x3aa7bc00,0xb23eb61f,0xbbd939a8,0xb8723b64,0xbaa73c00,0x323e361f,0x3bd9b9a8,0x3872bb64,0xb8728000,0xbbd93b64,0xb23e39a8,0x3aa7b61f,
0x361f8000,0x3b64b9a8,0x3b64bc00,0x361fb9a8,0xb61f8000,0xbb6439a8,0xbb643c00,0xb61f39a8,0x3b64bc00,0x361fb9a8,0xb61f8000,0xbb6439a8,0xbb643c00,0xb61f39a8,0x361f8000,0x3b64b9a8,
0xbbd93c00,0xbaa73b64,0xb87239a8,0xb23e361f,0xb23e8000,0xb872361f,0xbaa739a8,0xbbd93b64,0x323e8000,0x3872b61f,0x3aa7b9a8,0x3bd9bb64,0xbbd93c00,0xbaa73b64,0xb87239a8,0xb23e361f,
0xb8723c00,0x3bd9b61f,0xb23eb9a8,0xbaa73b64,0x3aa78000,0x323ebb64,0xbbd939a8,0x3872361f,0x3aa78000,0x323ebb64,0xbbd939a8,0x3872361f,0x3872bc00,0xbbd9361f,0x323e39a8,0x3aa7bb64,
0xb9a83c00,0x39a80000,0x39a8bc00,0xb9a88000,0xb9a83c00,0x39a88000,0x39a8bc00,0xb9a88000,0x39a88000,0x39a8bc00,0xb9a88000,0xb9a83c00,0x39a80000,0x39a8bc00,0xb9a88000,0xb9a83c00,
0xbbd98000,0x3aa7361f,0xb872b9a8,0x323e3b64,0xb23e3c00,0x3872bb64,0xbaa739a8,0x3bd9b61f,0xb23e3c00,0x3872bb64,0xbaa739a8,0x3bd9b61f,0x3bd98000,0xbaa7b61f,0x387239a8,0xb23ebb64,
0x361fbc00,0xbb6439a8,0x3b640000,0xb61fb9a8,0xb61f3c00,0x3b64b9a8,0xbb648000,0x361f39a8,0xbb648000,0x361f39a8,0x361fbc00,0xbb6439a8,0x3b648000,0xb61fb9a8,0xb61f3c00,0x3b64b9a8,
0x38728000,0x3bd93b64,0x323e39a8,0xbaa7b61f,0xbaa7bc00,0x323eb61f,0x3bd939a8,0x38723b64,0x3aa73c00,0xb23e361f,0xbbd9b9a8,0xb872bb64,0x38728000,0x3bd93b64,0x323e39a8,0xbaa7b61f,
0x39a88000,0x39a83c00,0xb9a88000,0xb9a8bc00,0x39a80000,0x39a83c00,0xb9a80000,0xb9a8bc00,0x39a83c00,0xb9a88000,0xb9a8bc00,0x39a88000,0x39a83c00,0xb9a88000,0xb9a8bc00,0x39a80000,
0x3bd93c00,0x3aa73b64,0x387239a8,0x323e361f,0x323e8000,0x3872361f,0x3aa739a8,0x3bd93b64,0xb23e8000,0xb872b61f,0xbaa7b9a8,0xbbd9bb64,0x3bd93c00,0x3aa73b64,0x387239a8,0x323e361f,
0xb61f8000,0xbb64b9a8,0xbb64bc00,0xb61fb9a8,0x361f8000,0x3b6439a8,0x3b643c00,0x361f39a8,0xbb64bc00,0xb61fb9a8,0x361f0000,0x3b6439a8,0x3b643c00,0x361f39a8,0xb61f8000,0xbb64b9a8,
0x0,0x0,0x0,0x0,0x0,0x0,0x0,0x0,0x3c003c00,0x3c003c00,0x3c003c00,0x3c003c00,0x3c003c00,0x3c003c00,0x3c003c00,0x3c003c00,
0x323e0000,0x3872361f,0x3aa739a8,0x3bd93b64,0x3bd93c00,0x3aa73b64,0x387239a8,0x323e361f,0x3bd93c00,0x3aa73b64,0x387239a8,0x323e361f,0xb23e0000,0xb872b61f,0xbaa7b9a8,0xbbd9bb64,
0xb61f0000,0xbb64b9a8,0xbb64bc00,0xb61fb9a8,0x361f0000,0x3b6439a8,0x3b643c00,0x361f39a8,0xbb64bc00,0xb61fb9a8,0x361f8000,0x3b6439a8,0x3b643c00,0x361f39a8,0xb61f0000,0xbb64b9a8,
0xbaa7bc00,0x323eb61f,0x3bd939a8,0x38723b64,0x38720000,0x3bd93b64,0x323e39a8,0xbaa7b61f,0x38728000,0x3bd93b64,0x323e39a8,0xbaa7b61f,0x3aa73c00,0xb23e361f,0xbbd9b9a8,0xb872bb64,
0x3c00,0x8000bc00,0x3c00,0x8000bc00,0x3c00,0x8000bc00,0x80003c00,0x8000bc00,0x3c000000,0xbc000000,0x3c008000,0xbc000000,0x3c008000,0xbc000000,0x3c008000,0xbc000000,
0xb23e3c00,0x3872bb64,0xbaa739a8,0x3bd9b61f,0xbbd90000,0x3aa7361f,0xb872b9a8,0x323e3b64,0x3bd90000,0xbaa7b61f,0x387239a8,0xb23ebb64,0xb23e3c00,0x3872bb64,0xbaa739a8,0x3bd9b61f,
0x361fbc00,0xbb6439a8,0x3b648000,0xb61fb9a8,0xb61f3c00,0x3b64b9a8,0xbb640000,0x361f39a8,0xbb640000,0x361f39a8,0x361fbc00,0xbb6439a8,0x3b640000,0xb61fb9a8,0xb61f3c00,0x3b64b9a8,
0x3aa78000,0x323ebb64,0xbbd939a8,0x3872361f,0xb8723c00,0x3bd9b61f,0xb23eb9a8,0xbaa73b64,0x3872bc00,0xbbd9361f,0x323e39a8,0x3aa7bb64,0x3aa70000,0x323ebb64,0xbbd939a8,0x3872361f,
0xb23e0000,0xb872361f,0xbaa739a8,0xbbd93b64,0xbbd93c00,0xbaa73b64,0xb87239a8,0xb23e361f,0xbbd93c00,0xbaa73b64,0xb87239a8,0xb23e361f,0x323e8000,0x3872b61f,0x3aa7b9a8,0x3bd9bb64,
0x0,0x8000,0x8000,0x8000,0x8000,0x8000,0x80008000,0x8000,0xbc003c00,0xbc003c00,0xbc003c00,0xbc003c00,0xbc003c00,0xbc003c00,0xbc003c00,0xbc003c00,
0x3aa7bc00,0xb23eb61f,0xbbd939a8,0xb8723b64,0xb8720000,0xbbd93b64,0xb23e39a8,0x3aa7b61f,0xb8728000,0xbbd93b64,0xb23e39a8,0x3aa7b61f,0xbaa73c00,0x323e361f,0x3bd9b9a8,0x3872bb64,
0x361f0000,0x3b64b9a8,0x3b64bc00,0x361fb9a8,0xb61f0000,0xbb6439a8,0xbb643c00,0xb61f39a8,0x3b64bc00,0x361fb9a8,0xb61f8000,0xbb6439a8,0xbb643c00,0xb61f39a8,0x361f0000,0x3b64b9a8,
0x323e3c00,0xb872bb64,0x3aa739a8,0xbbd9b61f,0x3bd98000,0xbaa7361f,0x3872b9a8,0xb23e3b64,0xbbd90000,0x3aa7b61f,0xb87239a8,0x323ebb64,0x323e3c00,0xb872bb64,0x3aa739a8,0xbbd9b61f,
0x80003c00,0xbc00,0x80003c00,0x8000bc00,0x80003c00,0xbc00,0x80003c00,0xbc00,0xbc000000,0x3c000000,0xbc008000,0x3c000000,0xbc008000,0x3c000000,0xbc008000,0x3c008000,
0xbaa78000,0xb23ebb64,0x3bd939a8,0xb872361f,0x38723c00,0xbbd9b61f,0x323eb9a8,0x3aa73b64,0xb872bc00,0x3bd9361f,0xb23e39a8,0xbaa7bb64,0xbaa70000,0xb23ebb64,0x3bd939a8,0xb872361f,
0xb61fbc00,0x3b6439a8,0xbb640000,0x361fb9a8,0x361f3c00,0xbb64b9a8,0x3b648000,0xb61f39a8,0x3b648000,0xb61f39a8,0xb61fbc00,0x3b6439a8,0xbb640000,0x361fb9a8,0x361f3c00,0xbb64b9a8,
0x39a80000,0x39a83c00,0xb9a80000,0xb9a8bc00,0x39a88000,0x39a83c00,0xb9a80000,0xb9a8bc00,0x39a83c00,0xb9a80000,0xb9a8bc00,0x39a88000,0x39a83c00,0xb9a80000,0xb9a8bc00,0x39a88000,
0x3aa70000,0x323e3b64,0xbbd9b9a8,0x3872b61f,0x38723c00,0xbbd9b61f,0x323eb9a8,0x3aa73b64,0x38723c00,0xbbd9b61f,0x323eb9a8,0x3aa73b64,0xbaa70000,0xb23ebb64,0x3bd939a8,0xb872361f,
0xbb640000,0x361fb9a8,0x361f3c00,0xbb64b9a8,0x3b640000,0xb61f39a8,0xb61fbc00,0x3b6439a8,0xb61fbc00,0x3b6439a8,0xbb640000,0x361fb9a8,0x361f3c00,0xbb64b9a8,0x3b648000,0xb61f39a8,
0xb23ebc00,0x38723b64,0xbaa7b9a8,0x3bd9361f,0x3bd90000,0xbaa7361f,0x3872b9a8,0xb23e3b64,0x3bd98000,0xbaa7361f,0x3872b9a8,0xb23e3b64,0x323e3c00,0xb872bb64,0x3aa739a8,0xbbd9b61f,
0xb9a83c00,0x39a88000,0x39a8bc00,0xb9a80000,0xb9a83c00,0x39a88000,0x39a8bc00,0xb9a88000,0x39a80000,0x39a8bc00,0xb9a80000,0xb9a83c00,0x39a88000,0x39a8bc00,0xb9a80000,0xb9a83c00,
0xbaa73c00,0x323e361f,0x3bd9b9a8,0x3872bb64,0xb8728000,0xbbd93b64,0xb23e39a8,0x3aa7b61f,0x38720000,0x3bd9bb64,0x323eb9a8,0xbaa7361f,0xbaa73c00,0x323e361f,0x3bd9b9a8,0x3872bb64,
0x3b64bc00,0x361fb9a8,0xb61f8000,0xbb6439a8,0xbb643c00,0xb61f39a8,0x361f8000,0x3b64b9a8,0xb61f0000,0xbb6439a8,0xbb643c00,0xb61f39a8,0x361f0000,0x3b64b9a8,0x3b64bc00,0x361fb9a8,
0x323e8000,0x3872b61f,0x3aa7b9a8,0x3bd9bb64,0xbbd93c00,0xbaa73b64,0xb87239a8,0xb23e361f,0x3bd9bc00,0x3aa7bb64,0x3872b9a8,0x323eb61f,0x323e0000,0x3872b61f,0x3aa7b9a8,0x3bd9bb64,
0xbaa70000,0xb23e3b64,0x3bd9b9a8,0xb872b61f,0xb8723c00,0x3bd9b61f,0xb23eb9a8,0xbaa73b64,0xb8723c00,0x3bd9b61f,0xb23eb9a8,0xbaa73b64,0x3aa78000,0x323ebb64,0xbbd939a8,0x3872361f,
0xb9a80000,0xb9a83c00,0x39a80000,0x39a8bc00,0xb9a88000,0xb9a83c00,0x39a80000,0x39a8bc00,0xb9a83c00,0x39a80000,0x39a8bc00,0xb9a88000,0xb9a83c00,0x39a88000,0x39a8bc00,0xb9a88000,
0x323ebc00,0xb8723b64,0x3aa7b9a8,0xbbd9361f,0xbbd90000,0x3aa7361f,0xb872b9a8,0x323e3b64,0xbbd98000,0x3aa7361f,0xb872b9a8,0x323e3b64,0xb23e3c00,0x3872bb64,0xbaa739a8,0x3bd9b61f,
0x3b640000,0xb61fb9a8,0xb61f3c00,0x3b64b9a8,0xbb640000,0x361f39a8,0x361fbc00,0xbb6439a8,0x361fbc00,0xbb6439a8,0x3b640000,0xb61fb9a8,0xb61f3c00,0x3b64b9a8,0xbb648000,0x361f39a8,
0x3aa73c00,0xb23e361f,0xbbd9b9a8,0xb872bb64,0x38728000,0x3bd93b64,0x323e39a8,0xbaa7b61f,0xb8720000,0xbbd9bb64,0xb23eb9a8,0x3aa7361f,0x3aa73c00,0xb23e361f,0xbbd9b9a8,0xb872bb64,
0x39a83c00,0xb9a88000,0xb9a8bc00,0x39a88000,0x39a83c00,0xb9a88000,0xb9a8bc00,0x39a80000,0xb9a80000,0xb9a8bc00,0x39a80000,0x39a83c00,0xb9a88000,0xb9a8bc00,0x39a88000,0x39a83c00,
0xb23e8000,0xb872b61f,0xbaa7b9a8,0xbbd9bb64,0x3bd93c00,0x3aa73b64,0x387239a8,0x323e361f,0xbbd9bc00,0xbaa7bb64,0xb872b9a8,0xb23eb61f,0xb23e0000,0xb872b61f,0xbaa7b9a8,0xbbd9bb64,
0xbb64bc00,0xb61fb9a8,0x361f0000,0x3b6439a8,0x3b643c00,0x361f39a8,0xb61f8000,0xbb64b9a8,0x361f0000,0x3b6439a8,0x3b643c00,0x361f39a8,0xb61f0000,0xbb64b9a8,0xbb64bc00,0xb61fb9a8,
};
__device__ __align__(1024) bf16 g_x1T[DM * XP];
__device__ __align__(1024) bf16 g_x2T[DM * XP];
__device__ __align__(1024) uint4 g_of[8][16][1280];
__device__ __align__(1024) float g_fs[2][SEQ];

#define TS_SMEM 0
#define TS_DECL
#define TS_ARG
#define TS_PASS
#define TS_PHASE(p)
#define TS(i)
#define TSX(row, i)
#define TS_BEGIN
#define TS_END

struct cplx { float r, i; };
__device__ __forceinline__ cplx cmul(cplx a, cplx b) {
    cplx o;
    o.r = fmaf(a.r, b.r, -a.i * b.i);
    o.i = fmaf(a.r, b.i, a.i * b.r);
    return o;
}
__device__ __forceinline__ cplx csq(cplx a) {
    cplx o;
    o.r = fmaf(a.r, a.r, -a.i * a.i);
    o.i = 2.f * a.r * a.i;
    return o;
}
__device__ __forceinline__ cplx cexp_p(float arl, float ai, float p) {
    float mag = ex2(arl * p);
    float ang = ai * p;
    float n = rintf(ang * 0.15915494309189535f);
    float r = fmaf(n, -6.2831854820251465f, ang);
    r = fmaf(n, 1.7484555e-7f, r);
    cplx o;
    o.r = mag * __cosf(r);
    o.i = mag * __sinf(r);
    return o;
}

__device__ __forceinline__ uint32_t pack2h(float lo, float hi) {
    uint32_t r;
    asm("cvt.rn.f16x2.f32 %0, %1, %2;" : "=r"(r) : "f"(hi), "f"(lo));
    return r;
}
__device__ __forceinline__ uint32_t hmul(uint32_t a, uint32_t b) { uint32_t d; asm("mul.rn.f16x2 %0, %1, %2;" : "=r"(d) : "r"(a), "r"(b)); return d; }
__device__ __forceinline__ uint32_t hfma(uint32_t a, uint32_t b, uint32_t c) { uint32_t d; asm("fma.rn.f16x2 %0, %1, %2, %3;" : "=r"(d) : "r"(a), "r"(b), "r"(c)); return d; }
__device__ __forceinline__ uint32_t hfms(uint32_t a, uint32_t b, uint32_t c) {
    uint32_t d;
    asm("{\n.reg .b32 n;\nneg.f16x2 n, %1;\nfma.rn.f16x2 %0, n, %2, %3;\n}" : "=r"(d) : "r"(a), "r"(b), "r"(c));
    return d;
}
__device__ __forceinline__ uint32_t hadd(uint32_t a, uint32_t b) { uint32_t d; asm("add.rn.f16x2 %0, %1, %2;" : "=r"(d) : "r"(a), "r"(b)); return d; }
__device__ __forceinline__ uint32_t hsub(uint32_t a, uint32_t b) { uint32_t d; asm("sub.rn.f16x2 %0, %1, %2;" : "=r"(d) : "r"(a), "r"(b)); return d; }
__device__ __forceinline__ uint4 ldg_tab(int tab, int t) { return ldg128((const uint4*)c_fft + t + tab * 128); }
__device__ __forceinline__ uint32_t u4(const uint4& v, int i) { return i == 0 ? v.x : i == 1 ? v.y : i == 2 ? v.z : v.w; }
struct cpair { uint32_t r, i; };
__device__ __forceinline__ cpair pmul(cpair p, uint32_t z) {
    const __half2 zv = *reinterpret_cast<const __half2*>(&z), pr = *reinterpret_cast<const __half2*>(&p.r), pi = *reinterpret_cast<const __half2*>(&p.i);
    const __half2 zr = __low2half2(zv), zi = __high2half2(zv);
    const __half2 a = __hfma2(__hneg2(pi), zi, __hmul2(pr, zr)), b = __hfma2(pi, zr, __hmul2(pr, zi));
    return {*reinterpret_cast<const uint32_t*>(&a), *reinterpret_cast<const uint32_t*>(&b)};
}
__device__ __forceinline__ uint32_t packz(cplx z) { return pack2h(z.r, z.i); }
__device__ __forceinline__ void wgmma_kg(float (&d)[24], uint64_t da, uint64_t db, int scale_d) {
    asm volatile("{\n.reg .pred p;\nsetp.ne.b32 p, %26, 0;\n"
                 "wgmma.mma_async.sync.aligned.m64n48k16.f32.f16.f16 "
                 "{%0,%1,%2,%3,%4,%5,%6,%7,%8,%9,%10,%11,%12,%13,%14,%15,%16,%17,%18,%19,%20,%21,%22,%23}, %24, %25, p, 1, 1, 1, 1;\n}\n"
                 : "+f"(d[0]), "+f"(d[1]), "+f"(d[2]), "+f"(d[3]), "+f"(d[4]), "+f"(d[5]), "+f"(d[6]), "+f"(d[7]), "+f"(d[8]), "+f"(d[9]),
                   "+f"(d[10]), "+f"(d[11]), "+f"(d[12]), "+f"(d[13]), "+f"(d[14]), "+f"(d[15]), "+f"(d[16]), "+f"(d[17]), "+f"(d[18]), "+f"(d[19]),
                   "+f"(d[20]), "+f"(d[21]), "+f"(d[22]), "+f"(d[23])
                 : "l"(da), "l"(db), "r"(scale_d));
}

struct SsmParams { const bf16 *lar, *aim, *cre, *cim, *logdt, *dskip; };
constexpr int KG_TABLES = 6 * 16384, KG_RES = 1664;
struct KgShared { uint32_t kmax[6], kexp[6]; float cinv[6]; };
struct KgParams { uint32_t l[3], a[3], r[3], i[3], dt, ds; };

__device__ __forceinline__ bool kg_is_hi(int warp) { return ((warp >> 1) ^ (warp >> 2)) & 1; }
__device__ __forceinline__ void kgen_load(KgParams& kp, int d0, int warp, int lane, const SsmParams& sp) {
    const int d = d0 + min(2 * (warp >> 2) + (warp & 1), 4), idx = d * (NMODE / 2) + lane;
    const bf16 *pr = kg_is_hi(warp) ? sp.cre : sp.lar, *pi = kg_is_hi(warp) ? sp.cim : sp.aim;
    kp.dt = __ldg((const uint16_t*)sp.logdt + d);
#pragma unroll
    for (int j = 0; j < 3; j++) {
        kp.l[j] = __ldg((const uint32_t*)sp.lar + idx + 32 * j); kp.a[j] = __ldg((const uint32_t*)sp.aim + idx + 32 * j);
        kp.r[j] = __ldg((const uint32_t*)pr + idx + 32 * j); kp.i[j] = __ldg((const uint32_t*)pi + idx + 32 * j);
    }
    kp.ds = __ldg((const uint16_t*)sp.dskip + d0 + min(warp >> 1, 4));
}

struct KgAnchors { uint32_t v[8]; };
__device__ __forceinline__ KgAnchors kg_anchor_lo(const KgParams& kp, uint32_t sel, float dt) {
    auto B = [&](uint32_t v) { return __uint_as_float(__byte_perm(v, 0u, sel)); };
    const float arl = -rbf(ex2(B(kp.l[0]) * 1.4426950408889634f)) * dt * 1.4426950408889634f, ai = B(kp.a[0]) * dt;
    const cplx z8 = cexp_p(arl, ai, 8.f), z16 = csq(z8), z24 = cmul(z16, z8), z32 = csq(z16), z64 = csq(z32), z128 = csq(z64), z192 = cmul(z128, z64);
    return {{pack2h(1.f, z8.r), pack2h(0.f, z8.i), pack2h(z16.r, z24.r), pack2h(z16.i, z24.i), packz(z32), packz(z64), packz(z128), packz(z192)}};
}
__device__ __forceinline__ KgAnchors kg_anchor_hi(const KgParams& kp, uint32_t sel, float dt, float cs) {
    auto B = [&](uint32_t v) { return __uint_as_float(__byte_perm(v, 0u, sel)); };
    const float arl = -rbf(ex2(B(kp.l[0]) * 1.4426950408889634f)) * dt * 1.4426950408889634f, ai = B(kp.a[0]) * dt;
    const cplx z1 = cexp_p(arl, -ai, 1.f), z2 = csq(z1), z4 = csq(z2), z256 = cexp_p(arl, -ai, 256.f), z512 = csq(z256), z1024 = csq(z512);
    const cplx H0 = {B(kp.r[0]) * cs, -B(kp.i[0]) * cs}, H4 = cmul(H0, z4);
    return {{pack2h(H0.r, H4.r), pack2h(H0.i, H4.i), packz(z1), packz(z2), packz(z256), packz(z512), packz(z1024), 0u}};
}

__device__ __forceinline__ void kgen_tables(KgParams& kp, uint32_t scr, uint32_t dump, KgShared* ks, int warp, int lane TS_ARG) {
    const int wg = warp >> 2, half = warp & 1, sw = lane & 7;
    const bool hi = kg_is_hi(warp);
    TS(23);
    const float dt = rbf(ex2(bf_lo(kp.dt) * 1.4426950408889634f));
    uint32_t sel = (wg == 2 && half) ? 0x3244u : 0x1044u;
    float cs = 0.f;
    KgAnchors an;
    if (hi) {
        uint32_t m = 0;
#pragma unroll
        for (int j = 0; j < 3; j++) m = __vmaxu2(m, __vmaxu2(kp.r[j] & 0x7FFF7FFFu, kp.i[j] & 0x7FFF7FFFu));
        m = __reduce_max_sync(~0u, max(m << 16, m & 0xFFFF0000u));
        const uint32_t e = min(max(__float_as_uint(2.f * dt * __uint_as_float(m)) >> 23, 2u), 252u);
        cs = 2.f * dt * __uint_as_float((253u - e) << 23);
        if (lane == 0) { ks->cinv[2 * wg + half] = __uint_as_float((e + 1u) << 23); ks->kmax[2 * wg + half] = 0u; }
        an = kg_anchor_hi(kp, sel, dt, cs);
    } else {
        an = kg_anchor_lo(kp, sel, dt);
    }
    float acc[24];
#pragma unroll
    for (int i = 0; i < 24; i++) acc[i] = 0.f;
    uint32_t tb = scr + 2 * wg * 16384 + lane * 128;
    uint64_t da = mkdesc(scr + 2 * wg * 16384, 4096, 1024, 1);
    int flip = 16384;
#pragma unroll 1
    for (int c = wg == 2 ? 1 : 0, step = wg == 2 ? 2 : 1; c < 6; c += step) {
        if (wg < 2) sel ^= 0x2200u;
        if (!hi) {
            if (c & 1) { kp.l[0] = kp.l[1]; kp.l[1] = kp.l[2]; kp.a[0] = kp.a[1]; kp.a[1] = kp.a[2]; }
            cpair p[4];
            p[0] = {an.v[0], an.v[1]}; p[1] = {an.v[2], an.v[3]};
            p[2] = pmul(p[0], an.v[4]); p[3] = pmul(p[1], an.v[4]);
#pragma unroll
            for (int j = 0; j < 4; j++) {
                cpair v[4];
#pragma unroll
                for (int i = 0; i < 4; i++) v[i] = j ? pmul(p[i], an.v[4 + j]) : p[i];
                const uint32_t a = tb + (((4 * half + j) ^ sw) << 4);
                sts128(a, make_uint4(v[0].r, v[1].r, v[2].r, v[3].r));
                sts128(a + 4096, make_uint4(v[0].i, v[1].i, v[2].i, v[3].i));
            }
            an = kg_anchor_lo(kp, sel, dt);
        } else {
            if (c & 1) {
#pragma unroll
                for (int j = 0; j < 2; j++) { kp.l[j] = kp.l[j + 1]; kp.a[j] = kp.a[j + 1]; kp.r[j] = kp.r[j + 1]; kp.i[j] = kp.i[j + 1]; }
            }
            const uint32_t h1 = an.v[2], h2 = an.v[3], h256 = an.v[4], h512 = an.v[5], h1024 = an.v[6];
            cpair p[11];
            p[0] = {an.v[0], an.v[1]};
            p[1] = pmul(p[0], h2); p[2] = pmul(p[0], h1); p[3] = pmul(p[1], h1);
            p[4] = pmul(p[0], h256); p[5] = pmul(p[1], h256); p[6] = pmul(p[0], h512); p[7] = pmul(p[4], h512);
            p[8] = pmul({__byte_perm(p[0].r, p[4].r, 0x5410), __byte_perm(p[0].i, p[4].i, 0x5410)}, h1024);
            p[9] = pmul(p[8], h512); p[10] = pmul(p[8], h1024);
#pragma unroll
            for (int j = 0; j < 3; j++) {
                const uint32_t a = tb + 8192 + (((3 * half + j) ^ sw) << 4);
                sts128(a, make_uint4(p[4 * j].r, p[4 * j + 1].r, p[4 * j + 2].r, p[j < 2 ? 4 * j + 3 : 10].r));
                sts128(a + 4096, make_uint4(p[4 * j].i, p[4 * j + 1].i, p[4 * j + 2].i, p[j < 2 ? 4 * j + 3 : 10].i));
            }
            an = kg_anchor_hi(kp, sel, dt, cs);
        }
        if (c == 0) TS(24);
        if (c == 3) TS(25);
        fence_async_smem();
        wg_wait<0>();
        named_bar(5 + wg, 128);
        wg_fence();
#pragma unroll
        for (int k = 0; k < 4; k++) wgmma_kg(acc, da + k * 128, da + 512 + k * 128, 1);
        wg_commit();
        tb += flip; da += flip >> 4; flip = -flip;
    }
    const bool up = warp & 2;
    const int r = 2 * wg + up, lo0 = 16 * half + (lane >> 2);
    const uint32_t o = dump + r * KG_RES + lo0 * 52 + 4 * (lane & 3);
    const float ci = __uint_as_float(lds32(s2u(&ks->cinv[r])));
    const float ds = (lane == 0 && warp <= 8 && !half) ? bf_lo(kp.ds) : 0.f;
    TS(26);
    wg_wait<0>();
    float v[12], m = 0.f;
#pragma unroll
    for (int j = 0; j < 12; j++) { v[j] = fmaf(ci, up ? acc[12 + j] : acc[j], j ? 0.f : ds); m = fmaxf(m, fabsf(v[j])); }
    const uint32_t mm = __reduce_max_sync(~0u, __float_as_uint(m));
    if (lane == 0) asm volatile("red.shared.max.u32 [%0], %1;" ::"r"(s2u(&ks->kmax[r])), "r"(mm) : "memory");
    named_bar(5 + wg, 128);
    const float mx = __uint_as_float(lds32(s2u(&ks->kmax[r]))) + (wg == 2 ? __uint_as_float(lds32(s2u(&ks->kmax[r ^ 1]))) : 0.f);
    const uint32_t e = min(max(__float_as_uint(mx) >> 23, 4u), 250u);
    const float sc = __uint_as_float((253u - e) << 23);
    if (lane == 0) ks->kexp[r] = e;
#pragma unroll
    for (int j = 0; j < 6; j++) sts32(o + (j & 1) * 416 + (j >> 1) * 16, pack2h(v[2 * j] * sc, v[2 * j + 1] * sc));
}
#define F_PPOS 0
#define F_STAG 4
__device__ __forceinline__ void wgmma_h64_rs(uint32_t (&d)[16], const uint4& a, uint64_t db, int scale_d) {
    asm volatile("{\n.reg .pred p;\nsetp.ne.b32 p, %21, 0;\n"
                 "wgmma.mma_async.sync.aligned.m64n64k16.f16.f16.f16 {%0,%1,%2,%3,%4,%5,%6,%7,%8,%9,%10,%11,%12,%13,%14,%15}, {%16,%17,%18,%19}, %20, p, 1, 1, 1;\n}\n"
                 : "+r"(d[0]), "+r"(d[1]), "+r"(d[2]), "+r"(d[3]), "+r"(d[4]), "+r"(d[5]), "+r"(d[6]), "+r"(d[7]), "+r"(d[8]), "+r"(d[9]),
                   "+r"(d[10]), "+r"(d[11]), "+r"(d[12]), "+r"(d[13]), "+r"(d[14]), "+r"(d[15])
                 : "r"(a.x), "r"(a.y), "r"(a.z), "r"(a.w), "l"(db), "r"(scale_d));
}
template <int TB>
__device__ __forceinline__ void wgmma_h32_rs(uint32_t (&d)[8], const uint4& a, uint64_t db, int scale_d) {
    asm volatile("{\n.reg .pred p;\nsetp.ne.b32 p, %13, 0;\n"
                 "wgmma.mma_async.sync.aligned.m64n32k16.f16.f16.f16 {%0,%1,%2,%3,%4,%5,%6,%7}, {%8,%9,%10,%11}, %12, p, 1, 1, %14;\n}\n"
                 : "+r"(d[0]), "+r"(d[1]), "+r"(d[2]), "+r"(d[3]), "+r"(d[4]), "+r"(d[5]), "+r"(d[6]), "+r"(d[7])
                 : "r"(a.x), "r"(a.y), "r"(a.z), "r"(a.w), "l"(db), "r"(scale_d), "n"(TB));
}
__device__ __forceinline__ void wgmma_s1(uint32_t (&d)[16], const uint4& a, uint64_t db, int scale_d) { wgmma_h64_rs(d, a, db, scale_d); }
__device__ __forceinline__ void wgmma_s1(uint32_t (&d)[8], const uint4& a, uint64_t db, int scale_d) { wgmma_h32_rs<1>(d, a, db, scale_d); }
__device__ __forceinline__ void wgmma_s4(float (&d)[32], const uint4& a, uint64_t db, uint32_t meta, int scale_d) {
    asm volatile("{\n.reg .pred p;\nsetp.ne.b32 p, %38, 0;\n"
                 "wgmma.mma_async.sp.sync.aligned.m64n64k32.f32.f16.f16 {%0,%1,%2,%3,%4,%5,%6,%7,%8,%9,%10,%11,%12,%13,%14,%15,%16,%17,%18,%19,%20,%21,%22,%23,%24,%25,%26,%27,%28,%29,%30,%31}, {%32,%33,%34,%35}, %36, %37, 0, p, 1, 1, 1;\n}\n"
                 : "+f"(d[0]), "+f"(d[1]), "+f"(d[2]), "+f"(d[3]), "+f"(d[4]), "+f"(d[5]), "+f"(d[6]), "+f"(d[7]), "+f"(d[8]), "+f"(d[9]), "+f"(d[10]), "+f"(d[11]), "+f"(d[12]), "+f"(d[13]), "+f"(d[14]), "+f"(d[15]), "+f"(d[16]), "+f"(d[17]), "+f"(d[18]), "+f"(d[19]), "+f"(d[20]), "+f"(d[21]), "+f"(d[22]), "+f"(d[23]), "+f"(d[24]), "+f"(d[25]), "+f"(d[26]), "+f"(d[27]), "+f"(d[28]), "+f"(d[29]), "+f"(d[30]), "+f"(d[31])
                 : "r"(a.x), "r"(a.y), "r"(a.z), "r"(a.w), "l"(db), "r"(meta), "r"(scale_d));
}
__device__ __forceinline__ void wgmma_s4(float (&d)[16], const uint4& a, uint64_t db, uint32_t meta, int scale_d) {
    asm volatile("{\n.reg .pred p;\nsetp.ne.b32 p, %22, 0;\n"
                 "wgmma.mma_async.sp.sync.aligned.m64n32k32.f32.f16.f16 {%0,%1,%2,%3,%4,%5,%6,%7,%8,%9,%10,%11,%12,%13,%14,%15}, {%16,%17,%18,%19}, %20, %21, 0, p, 1, 1, 1;\n}\n"
                 : "+f"(d[0]), "+f"(d[1]), "+f"(d[2]), "+f"(d[3]), "+f"(d[4]), "+f"(d[5]), "+f"(d[6]), "+f"(d[7]), "+f"(d[8]), "+f"(d[9]), "+f"(d[10]), "+f"(d[11]), "+f"(d[12]), "+f"(d[13]), "+f"(d[14]), "+f"(d[15])
                 : "r"(a.x), "r"(a.y), "r"(a.z), "r"(a.w), "l"(db), "r"(meta), "r"(scale_d));
}

__device__ __forceinline__ uint32_t& u4r(uint4& v, int i) { return i == 0 ? v.x : i == 1 ? v.y : i == 2 ? v.z : v.w; }

template <int NC>
__device__ __forceinline__ void fft_stage(const uint32_t (&u)[2][4], int c, uint32_t eo, int w, int lane) {
    const int mi = lane >> 3, mj = lane & 7;
    const uint32_t a = eo + (8 * w + mj) * 128 + (((4 * c + mi) ^ mj) << 4);
    stsm_x4(a, hadd(u[0][0], u[1][0]), hadd(u[0][1], u[1][1]), hadd(u[0][2], u[1][2]), hadd(u[0][3], u[1][3]));
    stsm_x4(NC == 2 ? a + 4096 : a ^ 64, hsub(u[0][0], u[1][0]), hsub(u[0][1], u[1][1]), hsub(u[0][2], u[1][2]), hsub(u[0][3], u[1][3]));
}
template <int NC>
__device__ __forceinline__ void kernel_stage(const uint4 (&ko)[2], uint32_t kt, uint32_t eo, int w, int lane) {
    uint32_t u[2][2][4];
#pragma unroll
    for (int h = 0; h < 2; h++)
#pragma unroll
        for (int j = 0; j < 4; j++) {
            const uint32_t a0 = kt + (u4(ko[h], j) & 0xFFFF), a1 = kt + (u4(ko[h], j) >> 16);
#pragma unroll
            for (int c = 0; c < 2; c++)
                asm volatile("{\n.reg .b16 a, b;\nld.shared.b16 a, [%1];\nld.shared.b16 b, [%2];\nmov.b32 %0, {a, b};\n}"
                             : "=r"(u[c][h][j]) : "r"(a0 + c * KG_RES), "r"(a1 + c * KG_RES) : "memory");
            if (NC == 1) u[0][h][j] = hadd(u[0][h][j], u[1][h][j]);
        }
#pragma unroll
    for (int c = 0; c < NC; c++) fft_stage<NC>(u[c], c, eo, w, lane);
}

template <int NC, bool SHEAR, class Mid>
__device__ __forceinline__ void fft_forward(const uint4 (&a1)[4], const uint4 (&tw)[4], uint32_t eo, uint32_t s2, uint32_t (&X)[NC][2][8], Mid mid) {
    uint32_t dr[8 * NC], di[8 * NC];
    const uint64_t de = mkdesc(eo, 4096, 1024, 1), d2 = mkdesc(s2, 16, 1024, 1);
    wg_fence();
    wgmma_s1(dr, a1[0], de, 0);
    wgmma_s1(di, a1[2], de + (NC == 2 ? 256 : 4), 0);
    wgmma_s1(dr, a1[1], de + 128, 1);
    wgmma_s1(di, a1[3], de + (NC == 2 ? 384 : 132), 1);
    wg_commit();
    mid();
    wg_wait<0>();
#pragma unroll
    for (int c = 0; c < NC; c++) {
        uint4 zr[2], zi[2];
#pragma unroll
        for (int p = 0; p < 2; p++)
#pragma unroll
            for (int i = 0; i < 4; i++) {
                const uint32_t r = dr[8 * c + 4 * p + i], m = di[8 * c + 4 * p + i], tr = u4(tw[p], i), ti = u4(tw[2 + p], i);
                if (SHEAR) {
                    const uint32_t r1 = hfma(tr, m, r), m1 = hfma(ti, r1, m);
                    u4r(zr[p], i) = hfma(tr, m1, r1); u4r(zi[p], i) = m1;
                } else {
                    u4r(zr[p], i) = hfms(m, ti, hmul(r, tr));
                    u4r(zi[p], i) = hfma(m, tr, hmul(r, ti));
                }
            }
        wg_fence();
        wgmma_h32_rs<0>(X[c][0], zi[0], d2 + 2, 0);
        wgmma_h32_rs<0>(X[c][1], zi[1], d2 + 6, 0);
        wgmma_h32_rs<0>(X[c][0], zr[0], d2, 1);
        wgmma_h32_rs<0>(X[c][1], zr[1], d2 + 4, 1);
        wg_commit();
    }
}

template <int NC, class Idle, class Ready, class Staged>
__device__ __forceinline__ void conv_wg(int ch0, int layer, uint32_t eo, uint32_t zb, uint32_t s23, uint32_t kexp, uint32_t epoch, uint32_t st, uint32_t sbar,
                                        int warp, int lane, uint4 (&a1)[4], uint4 (&tw)[4], Idle idle, Ready ready, Staged staged TS_ARG) {
    const int wg = warp >> 2, w = warp & 3, t = 32 * w + lane, g = lane >> 2, q = lane & 3, mi = lane >> 3, mj = lane & 7;
    auto F = [](uint32_t x) { return __uint_as_float(x); };
    uint32_t KH[NC][2][8];
    TS(2);
    fft_forward<NC, false>(a1, tw, eo, s23, KH, [] {});
    named_bar(1 + wg, 128);
    uint4 a4[4];
#pragma unroll
    for (int i = 0; i < 4; i++) { tw[i] = ldg_tab(4 + i, t); if (NC == 2) a4[i] = ldg_tab(12 + i, t); }
    wg_wait<0>();
    TS(4);
    idle();
    uint2 x[NC][2][2];
    const int ra[2] = {16 * (8 * w + g) + 4 * q, 16 * (63 - 8 * w - g) + 4 * q};
    if (NC == 1) {
        uint4 s[8];
        TS(1);
#pragma unroll
        for (int i = 0; i < 8; i++) s[i] = make_uint4(layer, 0, 0, 0);
        int spin = 0;
        uint32_t bad;
        do {
            bad = 0;
#pragma unroll
            for (int i = 0; i < 8; i++)
                if (((s[i].x ^ layer) & 1u) == 0) s[i] = ld_ll4((const uint4*)(g_fs[i & 1] + 1024 * ((i >> 1) & 1) + ra[i >> 2]));
#pragma unroll
            for (int i = 0; i < 8; i++) bad |= ~(s[i].x ^ layer);
        } while ((bad & 1u) && ++spin < (1 << 18));
#pragma unroll
        for (int i = 0; i < 8; i++) sts128(st + i * 2048 + t * 16, s[i]);
        __syncwarp();
        if (lane == 0) mbar_arrive(sbar + 8 * w);
#pragma unroll
        for (int i = 0; i < 4; i++) a4[i] = ldg_tab(12 + i, t);
        TS(14);
    }
    ready();
    TS(5);
    auto xload = [&](int i) {
        const unsigned long long v = ld_ll((const unsigned long long*)(g_x1T + (size_t)(ch0 + (i >> 2)) * XP + 1024 * (i & 1) + ra[(i >> 1) & 1]));
        x[i >> 2][(i >> 1) & 1][i & 1] = make_uint2((uint32_t)v, (uint32_t)(v >> 32));
    };
#pragma unroll
    for (int i = 0; i < 4 * NC; i++) xload(i);
    if (F_PPOS == 0) staged();
    TS(6);
    for (int spin = 0; spin < (1 << 18); spin++) {
        uint32_t bad = 0;
#pragma unroll
        for (int i = 0; i < 4 * NC; i++) bad |= ~(x[i >> 2][(i >> 1) & 1][i & 1].x ^ layer);
        if (!(bad & 1u)) break;
#pragma unroll
        for (int i = 0; i < 4 * NC; i++) if (((x[i >> 2][(i >> 1) & 1][i & 1].x ^ layer) & 1u) == 0) xload(i);
    }
    __syncwarp();
    TS(26);
    if (NC == 2) mbar_wait(sbar + 8 * w, 0);
    {
        uint4 s[2][2][2];
        uint32_t u[NC][2][4];
#pragma unroll
        for (int h = 0; h < 2; h++) {
            if (NC == 1 || h == 0) {
#pragma unroll
                for (int i = 4 * h; i < (NC == 1 ? 4 * h + 4 : 8); i++) s[i >> 2][(i >> 1) & 1][i & 1] = lds128(st + i * 2048 + t * 16);
            }
            if (h == 0) TS(7);
#pragma unroll
            for (int c = 0; c < NC; c++)
#pragma unroll
                for (int j = 0; j < 4; j++) {
                    const uint4 &a = s[h][j >> 1][0], &b = s[h][j >> 1][1];
                    const uint32_t xv = (j & 1) ? x[c][h][j >> 1].y : x[c][h][j >> 1].x;
                    u[c][h][j] = pack2h(fmaf(bf_lo(xv), F(u4(a, 2 * (j & 1))), F(u4(b, 2 * (j & 1)))), fmaf(bf_hi(xv), F(u4(a, 2 * (j & 1) + 1)), F(u4(b, 2 * (j & 1) + 1))));
                }
        }
#pragma unroll
        for (int c = 0; c < NC; c++) fft_stage<NC>(u[c], c, eo, w, lane);
    }
    TS(8);
    fence_async_smem();
    TS(9);
    if (F_PPOS == 1) staged();
    named_bar(1 + wg, 128);
    uint32_t X[NC][2][8], Y[NC][2][8];
    fft_forward<NC, true>(a1, tw, eo, s23, X, [&] { TS(3); if (F_PPOS == 2) staged(); if (F_STAG >= 2 && NC == 2 && wg == 1) named_bar(10 + w, 64); });
    if (F_STAG == 2 && NC == 2 && wg == 0) asm volatile("bar.arrive %0, 64;" ::"r"(10 + w) : "memory");
    TS(10);
    const uint64_t d3 = mkdesc(s23 + 4096, 16, 1024, 1);
#pragma unroll
    for (int c = 0; c < NC; c++) {
        wg_wait<NC - 1>();
        TS(11 + c);
        uint4 pr[2], pi[2];
#pragma unroll
        for (int i = 0; i < 4; i++) {
            const uint32_t er = X[c][0][i], ei = X[c][0][4 + i], orr = X[c][1][i], oi = X[c][1][4 + i];
            const uint32_t ar = KH[c][0][i], ai = KH[c][0][4 + i], br = KH[c][1][i], bi = KH[c][1][4 + i];
            u4r(pr[0], i) = hfms(bi, oi, hfma(br, orr, hfms(ai, ei, hmul(ar, er))));
            u4r(pi[0], i) = hfma(bi, orr, hfma(br, oi, hfma(ai, er, hmul(ar, ei))));
            u4r(pr[1], i) = hfms(ai, oi, hfma(ar, orr, hfms(bi, ei, hmul(br, er))));
            u4r(pi[1], i) = hfma(ai, orr, hfma(ar, oi, hfma(bi, er, hmul(br, ei))));
        }
        if (F_STAG == 3 + c && NC == 2 && wg == 0) asm volatile("bar.arrive %0, 64;" ::"r"(10 + w), "r"(pr[0].x ^ pr[1].w ^ pi[0].y ^ pi[1].z) : "memory");
        wg_fence();
        wgmma_h32_rs<0>(Y[c][0], pr[0], d3, 0);
        wgmma_h32_rs<0>(Y[c][1], pr[1], d3 + 4, 0);
        wgmma_h32_rs<0>(Y[c][0], pi[0], d3 + 2, 1);
        wgmma_h32_rs<0>(Y[c][1], pi[1], d3 + 6, 1);
        wg_commit();
    }
#pragma unroll
    for (int c = 0; c < NC; c++) {
        if (c + 1 < NC) wg_wait<1>(); else wg_wait<0>();
        TS(13 + c);
        uint32_t zr[2][4], zi[2][4];
#pragma unroll
        for (int p = 0; p < 2; p++)
#pragma unroll
            for (int i = 0; i < 4; i++) {
                const uint32_t r = Y[c][p][i], m = Y[c][p][4 + i], tr = u4(tw[p], i), ti = u4(tw[2 + p], i);
                const uint32_t r1 = hfms(tr, m, r), m1 = hfms(ti, r1, m);
                zr[i & 1][2 * p + (i >> 1)] = hfms(tr, m1, r1);
                zi[i & 1][2 * p + (i >> 1)] = m1;
            }
        const int kr = 4 * (mj >> 1) + (mj & 1) + 2 * (mj >> 2), ki = kr ^ 2;
#pragma unroll
        for (int h = 0; h < 2; h++) {
            const uint32_t a = zb + (2 * w + h) * 2048;
            stsm_x4(a + ki * 128 + (((4 * c + mi) ^ (ki & 7)) << 4), zi[h][0], zi[h][1], zi[h][2], zi[h][3]);
            stsm_x4(a + kr * 128 + (((4 * c + mi) ^ (kr & 7)) << 4), zr[h][0], zr[h][1], zr[h][2], zr[h][3]);
        }
    }
    TS(15);
    fence_async_smem();
    TS(16);
    named_bar(1 + wg, 128);
    TS(17);
    float acc[16 * NC];
    const uint64_t dz = mkdesc(zb, 4096, 1024, 1);
    wg_fence();
#pragma unroll
    for (int ks = 0; ks < 4; ks++) wgmma_s4(acc, a4[ks], dz + ks * 256, 0x44EEEE44u, ks > 0);
    wg_commit();
    uint32_t oscale[NC];
#pragma unroll
    for (int c = 0; c < NC; c++) oscale[c] = (lds32(kexp + 4 * c) + 3u) * 0x00800080u;
    const uint32_t fb = ~lds32(epoch) & 1u, keep = layer ? 0u : ~0u;
    wg_wait<0>();
    TS(18);
#pragma unroll
    for (int c = 0; c < NC; c++) {
        uint32_t r[2][4];
#pragma unroll
        for (int j = 0; j < 4; j++) {
            const float* d = acc + 4 * (4 * c + j);
            const uint32_t y0 = pack2(d[0] + d[2], d[1] + d[3]), y1 = pack2(d[0] - d[2], d[1] - d[3]);
            asm("fma.rn.bf16x2 %0, %1, %2, %3;" : "=r"(r[0][j]) : "r"(y0), "r"(oscale[c]), "r"(keep & ((j & 1) ? x[c][0][j >> 1].y : x[c][0][j >> 1].x)));
            asm("fma.rn.bf16x2 %0, %1, %2, %3;" : "=r"(r[1][j]) : "r"(y1), "r"(oscale[c]), "r"(keep & ((j & 1) ? x[c][1][j >> 1].y : x[c][1][j >> 1].x)));
        }
#pragma unroll
        for (int h = 0; h < 2; h++) {
            if (layer == 0) {
                bf16* dst = g_x2T + (size_t)(ch0 + c) * XP + ra[h];
                *(uint2*)dst = make_uint2(r[h][0], r[h][1]);
                *(uint2*)(dst + 1024) = make_uint2(r[h][2], r[h][3]);
            } else {
                st_ll4(&g_of[ch0 / 80][ra[h] >> 6][(ch0 % 80 + c) * 16 + ((ra[h] >> 2) & 15)], (r[h][0] & ~1u) | fb, r[h][1], r[h][2], r[h][3]);
            }
        }
    }
    TS(19);
}

#define Q_SCHED 3
#define Q_WAITFOR(it) (Q_SCHED == 0 ? (it) - 2 : Q_SCHED == 1 ? ((it) == 3 ? 1 : 0) : Q_SCHED == 2 ? -1 : (it) - 1)
#define Q_S0 8
#define A_HPOS 1
#define A_CSPRE 2
#define R_CONS 192
#define F_PRE 4
#define T_PF 1
#define K_CSUN 1
constexpr int K_CSU = K_CSUN;
#define G_MAP 1
#define O_TPOS 6
#define O_PASS 0
#define O_DEPTH 3
#define Q_SP 2
#define X_HINT 1
#define S_FIRST 1
constexpr int Q_ST = 4;
constexpr int Q_AB = 16384, Q_BB = 30720, Q_SB = Q_AB + Q_BB;
constexpr int Q_EROW = 336;
constexpr int Q_ESLOT = 8 * Q_EROW;
constexpr int Q_EOFF = Q_ST * Q_SB;
constexpr int Q_KG = 2 * Q_SB;
static_assert(3 * Q_ESLOT <= 8192 && Q_KG + KG_TABLES <= Q_EOFF + 4096, "exchange slots, kernel generation");
constexpr int F_EO = Q_EOFF, F_S23 = F_EO + 2 * 8192 + 4096, Q_KDUMP = F_S23 + 8192;
constexpr int Q_SMEM = Q_KDUMP + 6 * KG_RES + TS_SMEM;
__host__ __device__ constexpr int w_grp(int j) { return j < 7 ? 2 * Q_SB + j * 12800 : 0; }
constexpr int W_RES = Q_AB, W_OUT = Q_SB + Q_AB;

constexpr int Q_WOT = Q_EOFF + 4096;

__device__ unsigned g_epoch;
__device__ __align__(1024) unsigned g_bar[4][16][32];
__device__ __align__(1024) uint4 g_wop[8][80][10][8];
__device__ __align__(1024) uint4 g_csp[8][16][96];
__device__ __align__(1024) uint4 g_stp[16][8][64];
__device__ __align__(1024) uint4 g_sp2[16][8][8][8];
__device__ __align__(1024) uint4 g_halo[128][2][5][32];

struct Bars { uint64_t full[Q_ST], empty[Q_ST], wfull[3], ex[7], res, go, qdone, prep, ardy, hdone, fdone, idx, att1, pass, wfree, soon[2], st[4], kfree, staged; };
constexpr int NBAR = sizeof(Bars) / 8;
__host__ __device__ constexpr int bar_count(int i) {
#define BAR_IS(f) (i == offsetof(Bars, f) / 8)
    return (i >= 4 && i < 8) ? 16 : (BAR_IS(go) || (i >= offsetof(Bars, att1) / 8 && i < offsetof(Bars, st) / 8)) ? 4 : BAR_IS(qdone) ? 8 : BAR_IS(prep) ? 96 :
           BAR_IS(hdone) ? 6 : BAR_IS(fdone) ? 3 : BAR_IS(kfree) ? 24 : BAR_IS(staged) ? 2 : 1;
}
__device__ __forceinline__ void grid_wait(const unsigned* c, int n, unsigned target, int lane) {
    const unsigned* p = c + 32 * min(lane, n - 1);
    unsigned v;
    int spin = 0;
    do { asm volatile("ld.relaxed.gpu.global.u32 %0, [%1];" : "=r"(v) : "l"(p) : "memory"); } while (!__all_sync(~0u, (int)(v - target) >= 0) && ++spin < (1 << 18));
    fence_acquire();
}
__device__ __forceinline__ void grid_arrive(unsigned* c) {
    fence_release();
    asm volatile("red.relaxed.gpu.global.add.u32 [%0], 1;" ::"l"(c) : "memory");
}

#define TMAP(n) ([] { const CUtensorMap* p_; asm volatile("{\n.reg .b64 t;\nmov.b64 t, fused_kernel_param_" #n ";\ncvta.param.u64 %0, t;\n}" : "=l"(p_)); return p_; }())
extern "C" __global__ void __launch_bounds__(384, 1)
fused_kernel(const SsmParams sp, const __grid_constant__ CUtensorMap mX0, const __grid_constant__ CUtensorMap mX1, const __grid_constant__ CUtensorMap mW,
             const __grid_constant__ CUtensorMap mWr,
             const __grid_constant__ CUtensorMap mRes0, const __grid_constant__ CUtensorMap mRes1, const __grid_constant__ CUtensorMap mOut,
             const __grid_constant__ CUtensorMap mWo, const __grid_constant__ CUtensorMap mFin, const __grid_constant__ CUtensorMap mResA) {
    extern __shared__ __align__(1024) char smraw[];
    __shared__ __align__(8) Bars s_bar[2];
    __shared__ __align__(16) float s_cs[240], s_mean[2][64], s_rstd[2][72];
    __shared__ KgShared s_kg;
    __shared__ uint32_t s_epoch;
    const uint32_t sb = s2u(smraw);
    int tid, warp, lane, bx, rank, blk, hg, rot, c0;
    int role;
    {
        const int c = blockIdx.x >> 1, d = c - 41, r = d >= 21 ? 3 : d >= 14 ? 2 : d >= 7 ? 1 : 0;
        const int gp = c < 4 ? 0 : c <= 40 ? (c + 7) & 7 : d - 7 * r + 1;
        const int k = c < 4 ? c : c <= 40 ? (c >> 3) + (gp == 0 ? 3 : gp >= 3 && gp < 7 ? 0 : -1) : (gp >= 3 ? 5 : 4) + r;
        role = G_MAP == 1 ? 16 * k + 2 * gp + (blockIdx.x & 1) : G_MAP == 2 ? 16 * gp + 2 * k + (blockIdx.x & 1) : blockIdx.x;
    }
    auto indices = [&] {
        asm volatile("mov.u32 %0, %%tid.x;" : "=r"(tid));
        asm volatile("mov.u32 %0, %1;" : "=r"(bx) : "r"(role));
        warp = __shfl_sync(~0u, tid >> 5, 0); lane = tid & 31;
        rank = bx & 1; blk = bx & 15; hg = bx >> 4;
        const int u = ((blk >> 1) + hg) & 7;
        rot = (5 * u) >> 2; c0 = 16 * (u & 3);
    };
    indices();
    TS_DECL;
    TS_BEGIN;
#define EPOCH lds32(s2u(&s_epoch))
    int layer = 0;
    uint32_t bars = s2u(s_bar);
#define BAR(f) (bars + (uint32_t)offsetof(Bars, f))
    auto chunk = [&](int it, int s0) {
        const int i = it < s0 ? it : it - 2;
        return (it >> 1) == (s0 >> 1) ? rot + (it & 1) : i < rot ? i : i + 2;
    };
    auto osrc_of = [&](int j) { return j == 0 ? hg : j - 1 < hg ? j - 1 : j; };
    auto issue_w = [&](uint32_t bb, int it, int lay) {
        const int half = rank;
        const int s = it & (Q_ST - 1);
        const uint32_t fb = bb + 8 * s, db = sb + s * Q_SB + Q_AB + half * 15360;
        const int k0 = chunk(it, Q_SP * lay) * 64 + half * 32;
#pragma unroll
        for (int p = 0; p < 3; p++) tma2d_mc(db + p * 4096, TMAP(3), p * DM + hg * 80, k0, fb, 3);
        tma3d_mc(db + 12288, TMAP(4), hg * 80 + 64, k0, 0, fb, 3);
    };
    auto issue_x = [&](int it) {
        const int s = it & (Q_ST - 1), kc = chunk(it, Q_SP * layer);
        mbar_expect(BAR(full) + 8 * s, Q_SB);
        tma3d(sb + s * Q_SB, TMAP(1) + layer, (layer ? blk : kc) * 64, (layer ? kc : blk) * 64, 0, BAR(full) + 8 * s);
    };
    {
        KgParams kp;
        kgen_load(kp, bx * 5, warp, lane, sp);
        if (warp < 8) {
            cluster_arrive_relaxed();
        } else {
            const int t2 = tid - 256;
            if (elect_one()) {
                if (warp < 10) { prefetch_tmap(TMAP(3)); prefetch_tmap(TMAP(4)); } else prefetch_tmap(warp == 10 ? TMAP(1) : TMAP(8));
                const uint32_t b0 = bars + (warp >= 10 ? sizeof(Bars) : 0);
                if (warp & 1) {
#pragma unroll
                    for (int i = 0; i < NBAR / 2; i++) mbar_init(b0 + i * 8, bar_count(i));
                } else {
#pragma unroll
                    for (int i = NBAR / 2; i < NBAR; i++) mbar_init(b0 + i * 8, bar_count(i));
                }
                fence_mbar_init();
            }
            __syncwarp();
            cluster_arrive_relaxed();
            TS(29);
            const uint32_t epoch0 = ldg32(&g_epoch);
            cluster_wait();
            TS(27);
            if (elect_one()) {
                if (warp < 10) {
                    issue_w(BAR(full), warp - 8, 0);
                } else if (warp == 10) {
                    issue_x(0); issue_x(1);
                    prefetch_l2((const char*)c_fft + bx * (sizeof(c_fft) / 128), sizeof(c_fft) / 128);
                } else {
                    mbar_expect(BAR(idx), 8192 + 6400);
                    asm volatile("cp.async.bulk.tensor.4d.shared::cluster.global.mbarrier::complete_tx::bytes [%0], [%1, {0, 0, %3, %4}], [%2];"
                                 ::"r"(sb + Q_WOT), "l"(TMAP(8)), "r"(BAR(idx)), "r"(10 * hg), "r"(5 * blk) : "memory");
                    bulk_g2s(sb + F_S23, c_fft + 18 * 512, 8192, BAR(idx));
                }
            }
            __syncwarp();
            if (t2 == 0) s_epoch = epoch0;
            TS(30);
        }
        indices();
        kgen_tables(kp, sb + Q_KG, sb + Q_KDUMP, &s_kg, warp, lane TS_PASS);
        if (warp < 8) cluster_wait();
        __syncwarp();
        if (lane == 0) { mbar_arrive_cta(BAR(kfree), 0); mbar_arrive_cta(BAR(kfree), 1); }
        if (warp >= 8) {
            const int t2 = tid - 256;
            float csum[10];
            if (t2 < 64) stg128(&g_sp2[blk][hg][0][0] + t2, make_uint4(0, 0, 0, 0));
            if (t2 >= 120) stg128((uint4*)g_fs + 8 * bx + t2 - 120, make_uint4(0, 0, 0, 0));
            if (t2 < 64) stg128(g_x1T + (size_t)(5 * bx + 4) * XP + 64 * (t2 >> 1) + 48 + 8 * (t2 & 1), make_uint4(0, 0, 0, 0));
#pragma unroll
            for (int i = 0; i < 3; i++)
                if (t2 + 128 * i < 320) stg128(&g_halo[bx][0][0][0] + t2 + 128 * i, make_uint4(0, 0, 0, 0));
            if (warp == 8) asm volatile("bar.arrive 13, 128;" ::: "memory"); else named_bar(13, 128);
            if (warp > 8) {
                const int hw = warp - 9, mi = lane >> 3, mj = lane & 7;
                mbar_wait(BAR(idx), 0);
                if (hw == 2 && elect_one()) { bulk_s2g(&g_wop[hg][5 * blk], sb + Q_WOT, 6400); bulk_commit(); }
                __syncwarp();
                mbar_wait(BAR(full), 0);
                mbar_wait(BAR(full) + 8, 0);
#pragma unroll
                for (int f = 0; f < 10; f++) csum[f] = 0.f;
#pragma unroll K_CSU
                for (int G = 0; G < 5; G++) {
                    const int row = c0 + 40 * rank + 8 * G + mj;
                    const uint32_t b = sb + (row >> 6) * Q_SB + Q_AB + ((row >> 5) & 1) * 15360;
                    uint32_t r[10];
                    ldsm_x4_t(r[0], r[1], r[2], r[3], b + hw * 4096 + (row & 31) * 128 + ((mi ^ mj) << 4));
                    ldsm_x4_t(r[4], r[5], r[6], r[7], b + hw * 4096 + (row & 31) * 128 + (((4 + mi) ^ mj) << 4));
                    ldsm_x2_t(r[8], r[9], b + 12288 + hw * 1024 + (row & 31) * 32 + (((mi & 1) ^ (mj >> 2)) << 4));
#pragma unroll
                    for (int f = 0; f < 10; f++) csum[f] += bf_lo(r[f]) + bf_hi(r[f]);
                }
                const int q = lane & 3;
                float t[3];
#pragma unroll
                for (int j = 0; j < 3; j++) {
                    float v[4];
#pragma unroll
                    for (int k = 0; k < 4; k++) v[k] = 4 * j + k < 10 ? csum[4 * j + k] : 0.f;
                    const float a0 = ((q & 2) ? v[2] : v[0]) + __shfl_xor_sync(~0u, (q & 2) ? v[0] : v[2], 2);
                    const float a1 = ((q & 2) ? v[3] : v[1]) + __shfl_xor_sync(~0u, (q & 2) ? v[1] : v[3], 2);
                    t[j] = ((q & 1) ? a1 : a0) + __shfl_xor_sync(~0u, (q & 1) ? a0 : a1, 1);
                }
                st_ll4(&g_csp[hg][blk][tid - 288], ~EPOCH & 1u, __float_as_uint(t[0]), __float_as_uint(t[1]), __float_as_uint(t[2]));
            }
        }
        TS(1);
    }

    uint4 fa1[4], ftw[4];
    auto conv_tables = [&] {
#pragma unroll
        for (int i = 0; i < 4; i++) { fa1[i] = ldg_tab(i, tid & 127); ftw[i] = ldg_tab(8 + i, tid & 127); }
    };
    auto conv_done = [&] {
        if (layer == 0) {
            named_bar(1 + (warp >> 2), 128);
            if ((tid & 127) == 0) {
                mbar_arrive(BAR(fdone));
                grid_arrive(g_bar[2][hg]);
            }
            __syncwarp();
        }
        TS(20);
    };
    if (warp >= 8) {
    asm volatile("setmaxnreg.dec.sync.aligned.u32 %0;" ::"n"(504 - 2 * R_CONS));
#pragma unroll 1
    for (; layer < 2; layer++, bars += sizeof(Bars)) {
        indices();
        TS_PHASE(2 * layer);
        if (warp == 8) {
            if (layer) {
                grid_wait(g_bar[2][0], 8, 48 * (EPOCH + 1), lane);
                mbar_wait(BAR(fdone) - sizeof(Bars), 0);
                fence_async_global();
                TS(1);
            }
            if (elect_one()) {
#pragma unroll 1
                for (int it = layer ? 0 : 2; it < 10; it++) {
                    if (it >= Q_ST) mbar_wait(BAR(empty) + 8 * (it & (Q_ST - 1)), ((it >> 2) - 1) & 1);
                    else if (layer == 0) mbar_wait(BAR(kfree), 0);
                    else if (it > 0 && Q_WAITFOR(it) >= 0) mbar_wait(BAR(full) + 8 * Q_WAITFOR(it), 0);
                    if (it == Q_ST + Q_SP * layer) mbar_wait(BAR(hdone), 0);
                    issue_x(it);
                    if (layer == 0 || it >= F_PRE) issue_w(BAR(full), it, layer);
                }
                if (T_PF) { prefetch_tmap(TMAP(5) + layer); prefetch_tmap(TMAP(7)); prefetch_tmap(TMAP(10)); }
                if (layer == 0) { mbar_wait(BAR(prep), 0); fence_async_global(); }
#pragma unroll 1
                for (int j = 0; j < 8; j++) {
                    const int b = (j + 1) >> 2;
                    const uint32_t fb = BAR(wfull) + 8 * b;
                    if (j == 0 || j == 3 || j == 7) {
                        mbar_wait(BAR(empty) + 8 * ((2 + b) & 3), b < 2);
                        TS(11 + b);
                        mbar_expect(fb, (b == 0 ? 3 : b == 1 ? 4 : 1) * 12800);
                    }
                    bulk_g2s_mc(sb + w_grp(j) + rank * 6400, &g_wop[hg][osrc_of(j) * 10 + rank * 5], 6400, fb, 3);
                }
                mbar_expect(BAR(res), 20480);
                if (layer) {
                    tma3d(sb + W_RES, TMAP(6), blk * 64, hg * 80, 0, BAR(res));
                } else {
#pragma unroll 1
                    for (int p = 0; p < 2; p++) {
                        tma3d(sb + W_RES + p * 10240, TMAP(10), hg * 80, blk * 64, p, BAR(res));
                        tma3d(sb + W_RES + p * 10240 + 8192, TMAP(5), hg * 80 + 64, blk * 64, p, BAR(res));
                    }
                }
            }
            __syncwarp();
        } else {
            const int ht = tid - 288, hw = warp - 9, mi = lane >> 3, mj = lane & 7, g = lane >> 2, q = lane & 3;
            auto F = [](uint32_t x) { return __uint_as_float(x); };
            auto U = [](float x) { return __float_as_uint(x); };
            const uint32_t lb = layer ^ 1, eb = ~EPOCH & 1u;
            mbar_wait(BAR(full) + 8 * Q_SP * layer, 0);
            mbar_wait(BAR(full) + 8 * Q_SP * layer + 8, 0);
            if (ht == 0) TSX(2, 2);
            uint32_t xf[3][20];
#pragma unroll
            for (int i = 0; i < 3; i++) {
                const int tile = min(hw + 3 * i, 7);
#pragma unroll
                for (int k = 0; k < 5; k++) {
                    const int ch = c0 + 16 * k + 8 * (mi >> 1), tok = 16 * (tile & 3) + 8 * (mi & 1);
                    const uint32_t a = sb + ((ch >> 6) + Q_SP * layer) * Q_SB + (tile >> 2) * 8192;
                    if (layer == 0) ldsm_x4(xf[i][4 * k], xf[i][4 * k + 1], xf[i][4 * k + 2], xf[i][4 * k + 3], a + (tok + mj) * 128 + ((((ch & 63) >> 3) ^ mj) << 4));
                    else ldsm_x4_t(xf[i][4 * k], xf[i][4 * k + 1], xf[i][4 * k + 2], xf[i][4 * k + 3], a + ((ch & 63) + mj) * 128 + (((tok >> 3) ^ mj) << 4));
                }
            }
            fence_async_smem();
            __syncwarp();
            if (lane == 0) { mbar_arrive_cta(BAR(hdone), 0); mbar_arrive_cta(BAR(hdone), 1); }
            if (ht == 0) TSX(2, 3);
            if (layer == 0) {
                if (hw == 2 && elect_one()) { bulk_wait(); fence_async_global(); grid_arrive(g_bar[3][hg]); }
                __syncwarp();
                mbar_wait(BAR(kfree), 0);
            }
            if (ht == 0) TSX(2, 8);
#pragma unroll 1
            for (int tile = hw; tile < 8; tile += 3) {
                float a[4] = {0.f, 0.f, 0.f, 0.f};
#pragma unroll
                for (int j = 0; j < 20; j++) {
                    const float lo = bf_lo(xf[0][j]), hi = bf_hi(xf[0][j]);
                    a[2 * (j & 1)] += lo + hi; a[2 * (j & 1) + 1] = fmaf(lo, lo, fmaf(hi, hi, a[2 * (j & 1) + 1]));
                    xf[0][j] = xf[1][j]; xf[1][j] = xf[2][j];
                }
#pragma unroll
                for (int j = 0; j < 4; j++) { a[j] += __shfl_xor_sync(~0u, a[j], 1); a[j] += __shfl_xor_sync(~0u, a[j], 2); }
                if (q == 0) st_ll4(&g_stp[blk][hg][8 * tile + g], (U(a[0]) & ~1u) | lb, U(a[1]), U(a[2]), U(a[3]));
            }
            if (ht == 0) TSX(2, 4);
            if (layer == 0) {
                float t[4] = {0.f, 0.f, 0.f, 0.f};
                uint4 v[16];
                int spin = 0;
                uint32_t bad;
                do {
                    bad = 0;
#pragma unroll
                    for (int j = 0; j < 16; j++) v[j] = ld_ll4(&g_csp[hg][j][ht]);
#pragma unroll
                    for (int j = 0; j < 16; j++) bad |= v[j].x ^ eb;
                } while ((bad & 1u) && ++spin < (1 << 18));
#pragma unroll
                for (int j = 0; j < 16; j++) { t[0] += F(v[j].y); t[1] += F(v[j].z); t[2] += F(v[j].w); }
#pragma unroll
                for (int j = 0; j < 3; j++) if (q + 4 * j < 10) s_cs[80 * hw + 20 * (g >> 1) + 2 * (q + 4 * j) + (g & 1)] = t[j];
                if (hw == 2) grid_wait(g_bar[3][0], 8, 16 * (EPOCH + 1), lane);
            }
            if (ht == 0) TSX(2, 15);
            if (ht < 80) {
                const bool halo = ht >= 64;
                const int p = halo ? (ht >> 3) & 1 : ht >> 5, i = halo ? (ht & 7) - 8 : 8 + 2 * (ht & 24) + (ht & 7);
                const uint4* src = &g_stp[halo && blk ? blk - 1 : blk][0][halo ? 32 * p + 24 + (ht & 7) : ht];
                uint4 v[8];
                int spin = 0;
                uint32_t bad;
                do {
                    bad = 0;
#pragma unroll
                    for (int j = 0; j < 8; j++) v[j] = ld_ll4(src + 64 * j);
#pragma unroll
                    for (int j = 0; j < 8; j++) bad |= v[j].x ^ lb;
                } while ((bad & 1u) && ++spin < (1 << 18));
                float t[4] = {0.f, 0.f, 0.f, 0.f};
#pragma unroll
                for (int j = 0; j < 8; j++) { t[0] += F(v[j].x); t[1] += F(v[j].y); t[2] += F(v[j].z); t[3] += F(v[j].w); }
                const uint32_t s0 = ln_finish_packed(t[0], t[1]), s1 = ln_finish_packed(t[2], t[3]);
                if (!halo) { s_mean[p][i - 8] = bf_hi(s0); s_mean[p][i] = bf_hi(s1); s_rstd[p][i] = frcp(bf_lo(s0)); }
                s_rstd[p][i + 8] = frcp(bf_lo(s1));
            }
            fence_acquire();
            mbar_arrive(BAR(prep));
            if (ht == 0) TSX(2, 5);
        }
        __syncwarp();
        TS_PHASE(2 * layer + 1);
        TS(0);
        indices();
        {
            const uint4 ko[2] = {ldg_tab(16, tid & 127), ldg_tab(17, tid & 127)};
            conv_tables();
            mbar_wait(BAR(att1), 0);
            kernel_stage<1>(ko, sb + Q_KDUMP + 4 * KG_RES, sb + F_EO + 2 * 8192, warp & 3, lane);
            fence_async_smem();
            named_bar(3, 128);
        }
        conv_wg<1>(5 * bx + 4, layer, sb + F_EO + 2 * 8192, sb + 2 * Q_SB, sb + F_S23, s2u(&s_kg.kexp[4]), s2u(&s_epoch), sb + 3 * Q_SB, BAR(st), warp, lane, fa1, ftw,
        [&] {
            if (warp == 9) {
                auto F = [](uint32_t x) { return __uint_as_float(x); };
                mbar_wait(BAR(soon) + 8 * (hg >> 2), 0);
                TS(23);
                const uint4* src = &g_sp2[blk][hg][0][0] + lane;
                uint4* dst = (uint4*)(g_fs[(lane >> 2) & 1] + 1024 * (hg >> 2) + 64 * blk + 16 * (hg & 3)) + (lane & 3);
                const bool up = lane & 8;
#pragma unroll 1
                for (int spin = 0; spin < (1 << 18); spin++) {
                    const uint4 a = ld_ll4(src), b = ld_ll4(src + 32);
                    const bool ok = !__any_sync(~0u, ~((a.x ^ layer) & (b.x ^ layer)) & 1u);
                    const float s0 = F(a.x) + F(b.x), q0 = F(a.y) + F(b.y), s1 = F(a.z) + F(b.z), q1 = F(a.w) + F(b.w);
                    float sm = (up ? s1 : s0) + __shfl_xor_sync(~0u, up ? s0 : s1, 8), sq = (up ? q1 : q0) + __shfl_xor_sync(~0u, up ? q0 : q1, 8);
                    sm += __shfl_xor_sync(~0u, sm, 16); sq += __shfl_xor_sync(~0u, sq, 16);
                    const float m = sm * (1.0f / DM), r = frsq(fmaxf(fmaf(sq, 1.0f / DM, fmaf(-m, m, 1e-5f)), 1e-5f));
                    const uint32_t v = __float_as_uint(lane & 16 ? -m * r : r);
                    const uint32_t v0 = __shfl_sync(~0u, v, 4 * lane), v1 = __shfl_sync(~0u, v, 4 * lane + 1), v2 = __shfl_sync(~0u, v, 4 * lane + 2), v3 = __shfl_sync(~0u, v, 4 * lane + 3);
                    if (ok && lane < 8) st_ll4(dst, (v0 & ~1u) | (layer ^ 1), v1, v2, v3);
                    if (ok) break;
                }
            }
            TS(25);
            mbar_wait(BAR(staged), 0);
        }, [&] { mbar_wait(BAR(ardy), 0); }, [&] {
            if (T_PF && tid == 352) prefetch_tmap(layer ? TMAP(9) : TMAP(2));
            if (layer == 0 && warp - 8 < F_PRE && elect_one()) { mbar_wait(BAR(wfree), 0); issue_w(BAR(full) + sizeof(Bars), warp - 8, 1); }
            __syncwarp();
        } TS_PASS);
        conv_done();
    }
    } else {
#pragma unroll 1
    for (; layer < 2; layer++, bars += sizeof(Bars)) {
    indices();
    TS_PHASE(2 * layer);
    const int wg = warp >> 2, w = warp & 3;
    const int mi = lane >> 3, mj = lane & 7, g = lane >> 2, q = lane & 3;
    TS(2);
    float acc[120];
#pragma unroll
    for (int i = 0; i < 120; i++) acc[i] = 0.f;
    auto release = [&](int it) {
        if (lane == 0) { mbar_arrive_cta(BAR(empty) + 8 * (it & (Q_ST - 1)), 0); mbar_arrive_cta(BAR(empty) + 8 * (it & (Q_ST - 1)), 1); }
    };
#pragma unroll 1
    for (int it = 0; it < 10; it++) {
        const int s = it & (Q_ST - 1);
        const uint32_t st = sb + s * Q_SB;
        const bool hold = wg == 1 && it == Q_S0;
        if (hold) {
            wg_wait<0>();
            release(it - 1);
            mbar_wait(BAR(go), 0);
        }
        mbar_wait(BAR(full) + 8 * (s), (it >> 2) & 1);
        if (it < 2) TS(3 + it);
        if (it == 6) TS(5);
        if (it == 9) TS(6);
        const uint64_t da = mkdesc(st + wg * 8192, 16, 1024, 1);
        const uint64_t db = mkdesc(st + Q_AB, 4096, 1024, 1);
        const uint64_t dr = mkdesc(st + Q_AB + 12288, 1024, 256, 3);
        if (layer == 0) {
            wg_fence();
#pragma unroll
            for (int ks = 0; ks < 4; ks++) {
                const int sc = 1;
                wgmma_n192<0, 1>(*(float(*)[96]) & acc[0], da + ks * 2, db + (ks >> 1) * 960 + (ks & 1) * 128, sc);
                wgmma_n48<0, 1>(*(float(*)[24]) & acc[96], da + ks * 2, dr + (ks >> 1) * 960 + (ks & 1) * 32, sc);
            }
            wg_commit();
        } else {
            wg_fence();
#pragma unroll
            for (int ks = 0; ks < 4; ks++) {
                const int sc = 1;
                wgmma_n192<1, 1>(*(float(*)[96]) & acc[0], da + ks * 128, db + (ks >> 1) * 960 + (ks & 1) * 128, sc);
                wgmma_n48<1, 1>(*(float(*)[24]) & acc[96], da + ks * 128, dr + (ks >> 1) * 960 + (ks & 1) * 32, sc);
            }
            wg_commit();
        }
        wg_wait<1>();
        if (it > 0 && !hold) release(it - 1);
    }
    if (wg == 0 && lane == 0) mbar_arrive(BAR(go));
    asm volatile("setmaxnreg.inc.sync.aligned.u32 %0;" ::"n"(R_CONS));
    mbar_wait(BAR(prep), 0);
    const uint32_t ob = layer ^ 1;
    const bool first = (blk == 0 && w == 0);
    const bool sel0 = (2 * q > g), sel1 = (2 * q + 1 > g);
    constexpr float SC = 0.22360679774997896f * 1.4426950408889634f;
    const float m0 = s_mean[wg][16 * w + g], m1 = s_mean[wg][8 + 16 * w + g];
    uint4 cs[3][5];
    auto cs_load = [&](int p) {
#pragma unroll
        for (int i = 0; i < 5; i++) cs[p][i] = lds128(s2u(&s_cs[80 * p + 20 * q + 4 * i]));
    };
    if (A_CSPRE >= 1) cs_load(1);
    if (A_CSPRE >= 2) cs_load(2);
    wg_wait<0>();
    if (A_CSPRE < 1) cs_load(1);
    if (A_CSPRE < 2) cs_load(2);
    TS(7);
    if (lane == 0) mbar_arrive(BAR(qdone));
    uint32_t ql[10], qh[10], kl[10], kh[10], vl[10], vh[10];
    auto fold = [&](int p, int f, int h) {
        const int j = (f < 8) ? 8 * p + f : 24 + 2 * p + (f - 8);
        const float c0 = __uint_as_float(u4(cs[p][f >> 1], 2 * (f & 1))), c1 = __uint_as_float(u4(cs[p][f >> 1], 2 * (f & 1) + 1));
        const float m = h ? m1 : m0;
        return pack2(fmaf(-m, c0, acc[4 * j + 2 * h]), fmaf(-m, c1, acc[4 * j + 2 * h + 1]));
    };
#pragma unroll
    for (int f = 0; f < 10; f++) { kh[f] = fold(1, f, 1); vh[f] = fold(2, f, 1); }
    {
        const uint32_t mk = w == 3 ? 1u : 0u;
        auto mark = [&](uint32_t& v) { v = (v & ~mk) | (ob & mk); };
        mark(kh[0]); mark(kh[5]); mark(vh[0]); mark(vh[4]); mark(vh[8]);
    }
    if (w == 3) {
        uint4* hp = &g_halo[bx][wg][0][lane];
        st_ll4(hp, kh[0], kh[1], kh[3], kh[4]); st_ll4(hp + 32, kh[5], kh[6], kh[8], kh[9]);
        st_ll4(hp + 64, vh[0], vh[1], vh[2], vh[3]); st_ll4(hp + 96, vh[4], vh[5], vh[6], vh[7]);
        st_ll4(hp + 128, vh[8], vh[9], kh[2], kh[7]);
    } else {
        const uint32_t a = sb + Q_EOFF + wg * 8192 + w * Q_ESLOT + mj * Q_EROW + mi * 16;
        stsm_x4(a, kh[0], kh[1], kh[3], kh[4]);
        stsm_x4(a + 64, kh[5], kh[6], kh[8], kh[9]);
        stsm_x4(a + 128, vh[0], vh[1], vh[2], vh[3]);
        stsm_x4(a + 192, vh[4], vh[5], vh[6], vh[7]);
        stsm_x4(a + 256, vh[8], vh[9], kh[2], kh[7]);
        __syncwarp();
        if (lane == 0) mbar_arrive(BAR(ex) + 8 * warp);
    }
    TS(9);
    cs_load(0);
#pragma unroll
    for (int f = 0; f < 10; f++) { kl[f] = fold(1, f, 0); vl[f] = fold(2, f, 0); }
#pragma unroll
    for (int f = 0; f < 10; f++) { ql[f] = fold(0, f, 0); qh[f] = fold(0, f, 1); }
    auto rs = [&](int i) { return __uint_as_float(lds32(s2u(&s_rstd[wg][16 * w + i]))); };
    const float kx0 = rs(2 * q + (sel0 ? 0 : 8)), kx1 = rs(2 * q + (sel1 ? 1 : 9)), ky0 = rs(2 * q + (sel0 ? 8 : 16)), ky1 = rs(2 * q + (sel1 ? 9 : 17));
    const float rx = SC * rs(8 + g), ry = SC * rs(16 + g), cx0 = rx * kx0, cx1 = rx * kx1, cy0 = ry * ky0, cy1 = ry * ky1;
    uint4 hv[5];
    const uint4* hp = &g_halo[bx - 1][wg][0][lane];
    auto prev = [&] {
        if (w > 0) {
            const uint32_t a = sb + Q_EOFF + wg * 8192 + (w - 1) * Q_ESLOT + mj * Q_EROW + mi * 16;
            mbar_wait(BAR(ex) + 8 * (warp - 1), 0);
            ldsm_x4(hv[0].x, hv[0].y, hv[0].z, hv[0].w, a);
            ldsm_x4(hv[1].x, hv[1].y, hv[1].z, hv[1].w, a + 64);
            ldsm_x4_t(hv[2].x, hv[2].y, hv[2].z, hv[2].w, a + 128);
            ldsm_x4_t(hv[3].x, hv[3].y, hv[3].z, hv[3].w, a + 192);
            ldsm_x2_t(hv[4].x, hv[4].y, a + 256);
            ldsm_x2(hv[4].z, hv[4].w, a + 288 - (lane >> 4) * 32);
        } else if (blk > 0) {
#pragma unroll
            for (int f = 0; f < 5; f++) hv[f] = ld_ll4(hp + 32 * f);
        } else {
#pragma unroll
            for (int f = 0; f < 5; f++) hv[f] = make_uint4(0, 0, 0, 0);
        }
    };
    if (A_HPOS == 0) prev();
    uint32_t vt[10][2];
#pragma unroll
    for (int f = 0; f < 10; f++) { vt[f][0] = movm_t(vl[f]); vt[f][1] = movm_t(vh[f]); }
    if (A_HPOS == 1) prev();
    TS(10);
    auto FA = [](int h) { return h == 0 ? 0 : h == 1 ? 3 : h == 2 ? 5 : 8; };
    auto FH = [](int h) { return h < 2 ? 2 : 7; };
    const uint32_t pm = (sel0 ? 0xFFFFu : 0u) | (sel1 ? 0xFFFF0000u : 0u);
    auto softmax = [&](float x0, float x1, float k0, float k1) {
        float mx = fmaxf(x0, x1);
        mx = fmaxf(mx, __shfl_xor_sync(~0u, mx, 1));
        mx = fmaxf(mx, __shfl_xor_sync(~0u, mx, 2));
        x0 = ex2(x0 - mx); x1 = ex2(x1 - mx);
        float sx = x0 + x1;
        sx += __shfl_xor_sync(~0u, sx, 1);
        sx += __shfl_xor_sync(~0u, sx, 2);
        const float ix = frcp(sx);
        return pack2(x0 * k0 * ix, x1 * k1 * ix);
    };
    uint32_t qm[4][2], py[4];
    float sl[4][2];
#pragma unroll
    for (int h = 0; h < 4; h++) {
        const int fa = FA(h), fb = fa + 1, fh = FH(h);
        const bool mine = (h & 1) ? (q >= 2) : (q < 2);
        qm[h][0] = mine ? ql[fh] : 0u; qm[h][1] = mine ? qh[fh] : 0u;
        float S1[4] = {0.f, 0.f, 0.f, 0.f}, S2[4] = {0.f, 0.f, 0.f, 0.f};
        mma16816(S1, ql[fa], qh[fa], ql[fb], qh[fb], kl[fa], kl[fb]); mma1688(S1, qm[h][0], qm[h][1], kl[fh]);
        mma16816(S2, ql[fa], qh[fa], ql[fb], qh[fb], kh[fa], kh[fb]); mma1688(S2, qm[h][0], qm[h][1], kh[fh]);
        sl[h][0] = S1[0]; sl[h][1] = S1[1];
        py[h] = softmax((sel0 ? S1[2] : S2[2]) * cy0, (sel1 ? S1[3] : S2[3]) * cy1, ky0, ky1);
    }
    TS(11);
    if (w == 0 && blk > 0) {
        int spin = 0;
        while (__any_sync(~0u, ((hv[0].x ^ ob) | (hv[1].x ^ ob) | (hv[2].x ^ ob) | (hv[3].x ^ ob) | (hv[4].x ^ ob)) & 1u) && ++spin < (1 << 18)) {
#pragma unroll
            for (int f = 0; f < 5; f++) hv[f] = ld_ll4(hp + 32 * f);
        }
#pragma unroll
        for (int f = 2; f < 4; f++) hv[f] = make_uint4(movm_t(hv[f].x), movm_t(hv[f].y), movm_t(hv[f].z), movm_t(hv[f].w));
        hv[4].x = movm_t(hv[4].x); hv[4].y = movm_t(hv[4].y);
    }
    const uint32_t kp[10] = {hv[0].x, hv[0].y, hv[4].z, hv[0].z, hv[0].w, hv[1].x, hv[1].y, hv[4].w, hv[1].z, hv[1].w};
    const uint32_t vp[10] = {hv[2].x, hv[2].y, hv[2].z, hv[2].w, hv[3].x, hv[3].y, hv[3].z, hv[3].w, hv[4].x, hv[4].y};
    TS(12);
    const uint4 ko[2] = {ldg_tab(16, tid & 127), ldg_tab(17, tid & 127)};
    const float bx0 = first && sel0 ? -INFINITY : 0.f, bx1 = first && sel1 ? -INFINITY : 0.f;
    float oacc[10][4];
#pragma unroll
    for (int h = 0; h < 4; h++) {
        const int fa = FA(h), fb = fa + 1, fh = FH(h);
        const bool mine = (h & 1) ? (q >= 2) : (q < 2);
        float S0[4] = {0.f, 0.f, 0.f, 0.f};
        mma16816(S0, ql[fa], qh[fa], ql[fb], qh[fb], kp[fa], kp[fb]); mma1688(S0, qm[h][0], qm[h][1], kp[fh]);
        const uint32_t px = softmax(fmaf(sel0 ? S0[0] : sl[h][0], cx0, bx0), fmaf(sel1 ? S0[1] : sl[h][1], cx1, bx1), kx0, kx1);
#pragma unroll
        for (int i = 0; i < 3; i++) {
            const int f = (i == 0) ? fa : (i == 1) ? fb : fh;
            float O[4] = {0.f, 0.f, 0.f, 0.f};
            mma16816(O, px & ~pm, py[h] & pm, 0u, py[h] & ~pm, vt[f][0], vt[f][1]);
            mma1688(O, px & pm, 0u, vp[f]);
            if (i < 2 || !(h & 1) || mine) { oacc[f][0] = O[0]; oacc[f][1] = O[1]; oacc[f][2] = O[2]; oacc[f][3] = O[3]; }
        }
    }
    TS(13);
    constexpr int ON = O_DEPTH + 2;
    uint4 of[ON][5];
    const uint32_t fb = (EPOCH ^ ob) & 1u;
    {
        uint4* dst = &g_of[hg][blk][160 * warp + lane];
#pragma unroll
        for (int k = 0; k < 5; k++) {
            of[0][k] = make_uint4((pack2(oacc[2 * k][0], oacc[2 * k][1]) & ~1u) | fb, pack2(oacc[2 * k][2], oacc[2 * k][3]),
                                  pack2(oacc[2 * k + 1][0], oacc[2 * k + 1][1]), pack2(oacc[2 * k + 1][2], oacc[2 * k + 1][3]));
            st_ll4(dst + 32 * k, of[0][k].x, of[0][k].y, of[0][k].z, of[0][k].w);
        }
    }
    if (wg == 1 && lane == 0) mbar_arrive(BAR(att1));
    TS(14);
    float aw[40];
    auto omma = [&](int j) {
        const uint64_t dm = mkdesc(sb + w_grp(j), 1280, 128, 0);
        wg_fence();
#pragma unroll
        for (int k = 0; k < 5; k++) wgmma_rs80(aw, of[j % ON][k], dm + k * 160, j + k > 0);
        wg_commit();
    };
    mbar_wait(BAR(wfull), 0);
    omma(0);
    named_bar(1 + wg, 128);
    kernel_stage<2>(ko, sb + Q_KDUMP + 2 * wg * KG_RES, sb + F_EO + wg * 8192, w, lane);
    TS(8);
    const uint4* osrc = &g_of[0][blk][160 * warp + lane];
    auto oload = [&](int j) {
        const uint4* p = osrc + osrc_of(j) * 20480;
#pragma unroll
        for (int k = 0; k < 5; k++) of[j % ON][k] = ld_ll4(p + 32 * k);
    };
    {
        const uint32_t* pp = &g_of[osrc_of(1 + min(lane, 6))][blk][160 * warp + 159].x;
        uint32_t v;
        int spin = 0;
        do { asm volatile("ld.relaxed.gpu.global.u32 %0, [%1];" : "=r"(v) : "l"(pp) : "memory"); } while (__any_sync(~0u, (v & 1u) != fb) && ++spin < (1 << 18));
    }
    TS(15);
    if (O_PASS && wg == 1) mbar_wait(BAR(pass), 0);
#pragma unroll
    for (int j = 1; j <= O_DEPTH; j++) oload(j);
    TS(16);
#pragma unroll
    for (int j = 1; j < 8; j++) {
        if (j == 3 || j == 7) mbar_wait(BAR(wfull) + 8 * ((j + 1) >> 2), 0);
        const uint4* f = of[j % ON];
        int spin = 0;
        while (__any_sync(~0u, ((f[0].x ^ fb) | (f[1].x ^ fb) | (f[2].x ^ fb) | (f[3].x ^ fb) | (f[4].x ^ fb)) & 1u) && ++spin < (1 << 18)) oload(j);
        if (j + O_DEPTH < 8) { wg_wait<1>(); oload(j + O_DEPTH); }
        if (j == 7 && lane == 0) mbar_arrive(BAR(soon) + 8 * wg);
        if (j == O_PASS && wg == 0 && lane == 0) mbar_arrive(BAR(pass));
        if (j == O_TPOS) { wg_wait<1>(); conv_tables(); }
        if (j == 1) TS(17);
        if (j == 5) TS(18);
        omma(j);
    }
    wg_wait<2>();
    uint32_t res[20];
    mbar_wait(BAR(res), 0);
    const uint32_t ta = (8 * (mi >> 1) + mj) * 128 + (((2 * w + (mi & 1)) ^ mj) << 4);
    if (layer == 0) {
        const int tok = 16 * w + 8 * (mi & 1) + mj;
#pragma unroll
        for (int k = 0; k < 4; k++)
            ldsm_x4(res[4 * k], res[4 * k + 1], res[4 * k + 2], res[4 * k + 3], sb + W_RES + wg * 10240 + tok * 128 + (((2 * k + (mi >> 1)) ^ mj) << 4));
        ldsm_x4(res[16], res[17], res[18], res[19], sb + W_RES + wg * 10240 + 8192 + tok * 32 + (((mi >> 1) ^ (mj >> 2)) << 4));
    } else {
#pragma unroll
        for (int k = 0; k < 5; k++) ldsm_x4_t(res[4 * k], res[4 * k + 1], res[4 * k + 2], res[4 * k + 3], sb + W_RES + wg * 10240 + k * 2048 + ta);
    }
    mbar_wait(BAR(qdone), 0);
    wg_wait<0>();
    TS(19);
#pragma unroll
    for (int i = 0; i < 20; i++) {
        const uint32_t y = pack2(aw[2 * i], aw[2 * i + 1]);
        asm("add.rn.bf16x2 %0, %0, %1;" : "+r"(res[i]) : "r"(y));
    }
    auto stage_out = [&] {
        const uint32_t mk = (g & 3) ? 0u : 0x00010001u;
#pragma unroll
        for (int k = 0; k < 5; k++) {
            uint32_t m[4];
#pragma unroll
            for (int i = 0; i < 4; i++) m[i] = (res[4 * k + i] & ~mk) | (mk & (0u - ob));
            stsm_x4_t(sb + W_OUT + wg * 10240 + k * 2048 + ta, m[0], m[1], m[2], m[3]);
        }
        fence_async_smem();
        named_bar(1 + wg, 128);
        if (w == 0 && elect_one()) {
            asm volatile("cp.async.bulk.tensor.2d.global.shared::cta.bulk_group [%0, {%2, %3}], [%1];"
                         ::"l"(TMAP(7)), "r"(sb + W_OUT + wg * 10240), "r"(1024 * wg + 64 * blk), "r"(hg * 80) : "memory");
            bulk_commit();
            mbar_arrive(BAR(staged));
        }
        __syncwarp();
        TS(20);
    };
    if (!S_FIRST) stage_out();
    {
        float sm[4] = {0.f, 0.f, 0.f, 0.f}, d0[4] = {0.f, 0.f, 0.f, 0.f}, d1[4] = {0.f, 0.f, 0.f, 0.f};
#pragma unroll
        for (int k = 0; k < 5; k++) {
            mma16816(sm, res[4 * k], res[4 * k + 1], res[4 * k + 2], res[4 * k + 3], 0x3F803F80u, 0x3F803F80u);
            mma16816(d0, res[4 * k], res[4 * k + 1], res[4 * k + 2], res[4 * k + 3], res[4 * k], res[4 * k + 2]);
            mma16816(d1, res[4 * k], res[4 * k + 1], res[4 * k + 2], res[4 * k + 3], res[4 * k + 1], res[4 * k + 3]);
        }
        if (q == (g >> 1))
            st_ll4(&g_sp2[blk][warp][hg][g], (__float_as_uint(sm[0]) & ~1u) | ob, __float_as_uint((g & 1) ? d0[1] : d0[0]), __float_as_uint(sm[2]),
                   __float_as_uint((g & 1) ? d1[3] : d1[2]));
    }
    TS(23);
    if (S_FIRST) stage_out();
    if (layer) {
#pragma unroll
        for (int k = 0; k < 5; k++) stsm_x4_t(sb + W_RES + wg * 10240 + k * 2048 + ta, res[4 * k], res[4 * k + 1], res[4 * k + 2], res[4 * k + 3]);
    }
    if (O_TPOS == 9) conv_tables();
    TS(22);
    TS_PHASE(2 * layer + 1);
    TS(0);
    indices();
    conv_wg<2>(5 * bx + 2 * (warp >> 2), layer, sb + F_EO + (warp >> 2) * 8192, sb + (warp >> 2) * Q_SB, sb + F_S23, s2u(&s_kg.kexp[2 * (warp >> 2)]),
               s2u(&s_epoch), sb + 3 * Q_SB, BAR(st), warp, lane, fa1, ftw, [&] {
        if ((warp & 3) == 0 && elect_one()) {
            asm volatile("cp.async.bulk.wait_group.read 0;" ::: "memory");
            if (layer == 0) { mbar_arrive_cta(BAR(wfree), 0); mbar_arrive_cta(BAR(wfree), 1); }
        }
        __syncwarp();
    }, [&] {
        if (warp == 0) {
            const bf16* pp = g_x1T + (size_t)(5 * bx + 4) * XP + 64 * lane + 60;
            mbar_wait(BAR(staged), 0);
            uint32_t v;
            int spin = 0;
            if (X_HINT) do { asm volatile("ld.relaxed.gpu.global.u32 %0, [%1];" : "=r"(v) : "l"(pp) : "memory"); } while (__any_sync(~0u, ~(v ^ layer) & 1u) && ++spin < (1 << 18));
            if (lane == 0) mbar_arrive(BAR(ardy));
        } else {
            mbar_wait(BAR(ardy), 0);
        }
    }, [] {} TS_PASS);
    conv_done();
    asm volatile("setmaxnreg.dec.sync.aligned.u32 168;");
    }
    named_bar(1 + (warp >> 2), 128);
    asm volatile("setmaxnreg.dec.sync.aligned.u32 %0;" ::"n"(504 - 2 * R_CONS));
    }
    indices();
    const int cq = 4 * (warp >> 1) + (lane & 3), tg = 8 * (warp & 1) + (lane >> 2);
    const uint32_t fb = ~EPOCH & 1u;
    uint2 xr[4][2];
    __syncthreads();
    if (tid < 320) {
#pragma unroll
        for (int i = 0; i < 8; i++) {
            const int ch = 4 * cq + (i >> 1);
            asm volatile("ld.shared.v2.u32 {%0, %1}, [%2];" : "=r"(xr[i >> 1][i & 1].x), "=r"(xr[i >> 1][i & 1].y)
                         : "r"(sb + W_RES + (i & 1) * 10240 + ch * 128 + (((tg >> 1) ^ (ch & 7)) << 4) + (tg & 1) * 8) : "memory");
        }
    }
    if (tid < 320) {
        const uint4* src = &g_of[hg][blk][64 * cq + tg];
        uint4 v[4];
#pragma unroll
        for (int i = 0; i < 4; i++) v[i] = make_uint4(~fb, 0, 0, 0);
        int spin = 0;
        while (true) {
#pragma unroll
            for (int i = 0; i < 4; i++) if ((v[i].x ^ fb) & 1u) v[i] = ld_ll4(src + 16 * i);
            if (!(((v[0].x ^ fb) | (v[1].x ^ fb) | (v[2].x ^ fb) | (v[3].x ^ fb)) & 1u) || ++spin >= (1 << 18)) break;
        }
        TS(21);
#pragma unroll
        for (int i = 0; i < 16; i++) asm("add.rn.bf16x2 %0, %0, %1;" : "+r"(u4r(v[i >> 2], i & 3)) : "r"((i & 1) ? xr[i >> 2][(i >> 1) & 1].y : xr[i >> 2][(i >> 1) & 1].x));
#pragma unroll
        for (int j = 0; j < 8; j++) {
            const uint32_t sel = (j & 2) ? 0x7632 : 0x5410;
            const int k = 2 * (j & 1) + (j >> 2);
            asm volatile("st.shared.v2.u32 [%0], {%1, %2};" ::"r"(sb + 2 * Q_SB + (16 * j + tg) * 160 + cq * 8),
                         "r"(__byte_perm(u4(v[0], k), u4(v[1], k), sel)), "r"(__byte_perm(u4(v[2], k), u4(v[3], k), sel)) : "memory");
        }
        fence_async_smem();
    }
    __syncthreads();
    if (warp == 0 && elect_one()) {
        asm volatile("cp.async.bulk.tensor.3d.global.shared::cta.bulk_group [%0, {%2, %3, 0}], [%1];" ::"l"(TMAP(9)), "r"(sb + 2 * Q_SB), "r"(80 * hg), "r"(16 * blk) : "memory");
        bulk_commit();
        asm volatile("cp.async.bulk.wait_group.read 0;" ::: "memory");
    }
    if (bx == 0 && tid == 0) g_epoch = EPOCH + 1;
    TS(22);
    TS_END;
}
typedef CUresult (*EncodeTiledFn)(CUtensorMap*, CUtensorMapDataType, cuuint32_t, void*, const cuuint64_t*, const cuuint64_t*, const cuuint32_t*,
                                  const cuuint32_t*, CUtensorMapInterleave, CUtensorMapSwizzle, CUtensorMapL2promotion, CUtensorMapFloatOOBfill);

static void make_map(EncodeTiledFn enc, CUtensorMap* m, const void* base, int rank, const cuuint64_t* dims, const cuuint64_t* strides,
                     const cuuint32_t* box, CUtensorMapSwizzle sw) {
    cuuint32_t es[4] = {1, 1, 1, 1};
    enc(m, CU_TENSOR_MAP_DATA_TYPE_BFLOAT16, rank, (void*)base, dims, strides, box, es, CU_TENSOR_MAP_INTERLEAVE_NONE, sw,
        sw == CU_TENSOR_MAP_SWIZZLE_128B ? CU_TENSOR_MAP_L2_PROMOTION_L2_128B : CU_TENSOR_MAP_L2_PROMOTION_NONE, CU_TENSOR_MAP_FLOAT_OOB_FILL_NONE);
}

template <typename... KArgs, typename... Args>
static void launch(void (*kern)(KArgs...), int grid, int block, int smem, int cluster, bool pdl, Args... args) {
    cudaLaunchConfig_t cfg = {};
    cfg.gridDim = dim3(grid); cfg.blockDim = dim3(block); cfg.dynamicSmemBytes = smem; cfg.stream = cudaStreamPerThread;
    cudaLaunchAttribute at[2];
    int n = 0;
    if (cluster > 1) { at[n].id = cudaLaunchAttributeClusterDimension; at[n].val.clusterDim.x = cluster; at[n].val.clusterDim.y = 1; at[n].val.clusterDim.z = 1; n++; }
    if (pdl) { at[n].id = cudaLaunchAttributeProgrammaticStreamSerialization; at[n].val.programmaticStreamSerializationAllowed = 1; n++; }
    cfg.attrs = at; cfg.numAttrs = n;
    cudaLaunchKernelEx(&cfg, kern, KArgs(args)...);
}

struct HostState {
    bool ready = false;
    const void* key[4] = {nullptr, nullptr, nullptr, nullptr};
    CUtensorMap mX[2], mRes[2], mW, mWr, mWo, mOut, mFin, mResA;
    bf16 *x1T, *x2T;
};

extern "C" void kernel_launch(void* const* d_in, const int* in_sizes, int n_in, void* d_out, int out_size) {
    const bf16* x = (const bf16*)d_in[0];
    const bf16* wqkv = (const bf16*)d_in[1];
    const bf16* wo = (const bf16*)d_in[2];
    const bf16* lar = (const bf16*)d_in[4];
    const bf16* aim = (const bf16*)d_in[5];
    const bf16* cre = (const bf16*)d_in[6];
    const bf16* cim = (const bf16*)d_in[7];
    const bf16* logdt = (const bf16*)d_in[8];
    const bf16* dskip = (const bf16*)d_in[9];
    static HostState hs;
    if (!hs.ready || hs.key[0] != wqkv || hs.key[1] != wo || hs.key[2] != x || hs.key[3] != d_out) {
        void* fn = nullptr;
        cudaDriverEntryPointQueryResult qr;
        cudaGetDriverEntryPoint("cuTensorMapEncodeTiled", &fn, cudaEnableDefault, &qr);
        EncodeTiledFn enc = (EncodeTiledFn)fn;
        cudaGetSymbolAddress((void**)&hs.x1T, g_x1T);
        cudaGetSymbolAddress((void**)&hs.x2T, g_x2T);
        {
            cuuint64_t d[3] = {DM, SEQ / 2, 2}, s[2] = {DM * 4, DM * 2};
            cuuint32_t b[3] = {64, 64, 2}, ba[3] = {64, 64, 1}, br[3] = {16, 64, 1};
            make_map(enc, &hs.mX[0], x, 3, d, s, b, CU_TENSOR_MAP_SWIZZLE_128B);
            make_map(enc, &hs.mResA, x, 3, d, s, ba, CU_TENSOR_MAP_SWIZZLE_128B);
            make_map(enc, &hs.mRes[0], x, 3, d, s, br, CU_TENSOR_MAP_SWIZZLE_32B);
            cuuint64_t d2[3] = {SEQ / 2, DM, 2}, s2[2] = {XP * 2, SEQ};
            cuuint32_t b2[3] = {64, 80, 2};
            make_map(enc, &hs.mX[1], hs.x2T, 3, d2, s2, b, CU_TENSOR_MAP_SWIZZLE_128B);
            make_map(enc, &hs.mRes[1], hs.x2T, 3, d2, s2, b2, CU_TENSOR_MAP_SWIZZLE_128B);
            cuuint64_t d3[2] = {SEQ, DM};
            make_map(enc, &hs.mOut, hs.x1T, 2, d3, s2, b2, CU_TENSOR_MAP_SWIZZLE_128B);
        }
        { cuuint64_t d[2] = {3 * DM, DM}, s[1] = {3 * DM * 2}; cuuint32_t b[2] = {64, 32};
          make_map(enc, &hs.mW, wqkv, 2, d, s, b, CU_TENSOR_MAP_SWIZZLE_128B); }
        { cuuint64_t d[3] = {DM, DM, 3}, s[2] = {3 * DM * 2, DM * 2}; cuuint32_t b[3] = {16, 32, 3};
          make_map(enc, &hs.mWr, wqkv, 3, d, s, b, CU_TENSOR_MAP_SWIZZLE_32B); }
        { cuuint64_t d[4] = {8, 8, DM / 8, DM / 8}, s[3] = {DM * 2, 16, DM * 16}; cuuint32_t b[4] = {8, 8, 10, 5};
          make_map(enc, &hs.mWo, wo, 4, d, s, b, CU_TENSOR_MAP_SWIZZLE_NONE); }
        { cuuint64_t d[3] = {DM, SEQ / 8, 8}, s[2] = {DM * 16, DM * 2}; cuuint32_t b[3] = {80, 16, 8};
          make_map(enc, &hs.mFin, d_out, 3, d, s, b, CU_TENSOR_MAP_SWIZZLE_NONE); }
        cudaFuncSetAttribute(fused_kernel, cudaFuncAttributeMaxDynamicSharedMemorySize, Q_SMEM);
        hs.key[0] = wqkv; hs.key[1] = wo; hs.key[2] = x; hs.key[3] = d_out;
        hs.ready = true;
    }
    const SsmParams sp = {lar, aim, cre, cim, logdt, dskip};
    launch(fused_kernel, 128, 384, Q_SMEM, 2, false, sp, hs.mX[0], hs.mX[1], hs.mW, hs.mWr, hs.mRes[0], hs.mRes[1], hs.mOut, hs.mWo, hs.mFin, hs.mResA);
}
```

```cpp
#include <cuda_runtime.h>
#include <cuda.h>
#include <cuda_bf16.h>
#include <cuda_fp16.h>
#include <stdint.h>

typedef __nv_bfloat16 bf16;

constexpr int SEQ = 2048;
constexpr int DM  = 640;
constexpr int XP  = SEQ + 64;
constexpr int NMODE = 192;

__device__ __forceinline__ uint32_t s2u(const void* p) { return (uint32_t)__cvta_generic_to_shared(p); }
__device__ __forceinline__ void mbar_init(uint32_t b, int c) { asm volatile("mbarrier.init.shared::cta.b64 [%0], %1;" ::"r"(b), "r"(c)); }
__device__ __forceinline__ void mbar_expect(uint32_t b, uint32_t bytes) { asm volatile("mbarrier.arrive.expect_tx.shared::cta.b64 _, [%0], %1;" ::"r"(b), "r"(bytes) : "memory"); }
__device__ __forceinline__ void mbar_arrive(uint32_t b) { asm volatile("mbarrier.arrive.shared::cta.b64 _, [%0];" ::"r"(b) : "memory"); }
__device__ __forceinline__ void mbar_arrive_cta(uint32_t b, uint32_t cta) {
    asm volatile("{\n.reg .b32 ra;\nmapa.shared::cluster.u32 ra, %0, %1;\nmbarrier.arrive.shared::cluster.b64 _, [ra];\n}" ::"r"(b), "r"(cta) : "memory");
}
__device__ __forceinline__ void mbar_wait(uint32_t b, uint32_t ph) {
#ifdef M_PLAIN
    asm volatile("{\n.reg .pred p;\nW: mbarrier.try_wait.parity.shared::cta.b64 p, [%0], %1;\n@!p bra W;\n}" ::"r"(b), "r"(ph) : "memory");
    return;
#endif
    asm volatile("{\n.reg .pred p;\n.reg .u32 n;\nmbarrier.try_wait.parity.shared::cta.b64 p, [%0], %1;\n@p bra D;\nmov.u32 n, 0;\n"
                 "W: mbarrier.try_wait.parity.shared::cta.b64 p, [%0], %1;\n@p bra D;\nadd.u32 n, n, 1;\nsetp.lt.u32 p, n, 4194304;\n@p bra W;\ntrap;\nD:\n}"
                 ::"r"(b), "r"(ph) : "memory");
}
__device__ __forceinline__ void fence_mbar_init() { asm volatile("fence.mbarrier_init.release.cluster;" ::: "memory"); }
__device__ __forceinline__ void cluster_sync() { asm volatile("barrier.cluster.arrive.aligned;\nbarrier.cluster.wait.aligned;" ::: "memory"); }
__device__ __forceinline__ void pdl_wait() { asm volatile("griddepcontrol.wait;" ::: "memory"); }
__device__ __forceinline__ void pdl_launch() { asm volatile("griddepcontrol.launch_dependents;" ::: "memory"); }
__device__ __forceinline__ void named_bar(int id, int n) { asm volatile("bar.sync %0, %1;" ::"r"(id), "r"(n) : "memory"); }
__device__ __forceinline__ void fence_async_smem() { asm volatile("fence.proxy.async.shared::cta;" ::: "memory"); }

__device__ __forceinline__ void tma2d(uint32_t dst, const CUtensorMap* m, int c0, int c1, uint32_t bar) {
    asm volatile("cp.async.bulk.tensor.2d.shared::cluster.global.mbarrier::complete_tx::bytes [%0], [%1, {%3, %4}], [%2];"
                 ::"r"(dst), "l"(m), "r"(bar), "r"(c0), "r"(c1) : "memory");
}
__device__ __forceinline__ void tma2d_mc(uint32_t dst, const CUtensorMap* m, int c0, int c1, uint32_t bar, uint16_t mask) {
    asm volatile("cp.async.bulk.tensor.2d.shared::cluster.global.mbarrier::complete_tx::bytes.multicast::cluster [%0], [%1, {%3, %4}], [%2], %5;"
                 ::"r"(dst), "l"(m), "r"(bar), "r"(c0), "r"(c1), "h"(mask) : "memory");
}
__device__ __forceinline__ void tma3d(uint32_t dst, const CUtensorMap* m, int c0, int c1, int c2, uint32_t bar) {
    asm volatile("cp.async.bulk.tensor.3d.shared::cluster.global.mbarrier::complete_tx::bytes [%0], [%1, {%3, %4, %5}], [%2];"
                 ::"r"(dst), "l"(m), "r"(bar), "r"(c0), "r"(c1), "r"(c2) : "memory");
}
__device__ __forceinline__ void tma3d_mc(uint32_t dst, const CUtensorMap* m, int c0, int c1, int c2, uint32_t bar, uint16_t mask) {
    asm volatile("cp.async.bulk.tensor.3d.shared::cluster.global.mbarrier::complete_tx::bytes.multicast::cluster [%0], [%1, {%3, %4, %5}], [%2], %6;"
                 ::"r"(dst), "l"(m), "r"(bar), "r"(c0), "r"(c1), "r"(c2), "h"(mask) : "memory");
}
__device__ __forceinline__ void bulk_g2s(uint32_t dst, const void* src, uint32_t bytes, uint32_t bar) {
    asm volatile("cp.async.bulk.shared::cluster.global.mbarrier::complete_tx::bytes [%0], [%1], %2, [%3];"
                 ::"r"(dst), "l"(src), "r"(bytes), "r"(bar) : "memory");
}
__device__ __forceinline__ void bulk_g2s_mc(uint32_t dst, const void* src, uint32_t bytes, uint32_t bar, uint16_t mask) {
    asm volatile("cp.async.bulk.shared::cluster.global.mbarrier::complete_tx::bytes.multicast::cluster [%0], [%1], %2, [%3], %4;"
                 ::"r"(dst), "l"(src), "r"(bytes), "r"(bar), "h"(mask) : "memory");
}
__device__ __forceinline__ void prefetch_l2(const void* p, uint32_t bytes) { asm volatile("cp.async.bulk.prefetch.L2.global [%0], %1;" ::"l"(p), "r"(bytes) : "memory"); }
__device__ __forceinline__ void prefetch_tmap(const CUtensorMap* m) { asm volatile("prefetch.tensormap [%0];" ::"l"(m) : "memory"); }

__device__ __forceinline__ void wg_fence() { asm volatile("wgmma.fence.sync.aligned;" ::: "memory"); }
__device__ __forceinline__ void wg_commit() { asm volatile("wgmma.commit_group.sync.aligned;" ::: "memory"); }
template <int N> __device__ __forceinline__ void wg_wait() { asm volatile("wgmma.wait_group.sync.aligned %0;" ::"n"(N) : "memory"); }
__device__ __forceinline__ uint64_t mkdesc(uint32_t addr, uint32_t lbo, uint32_t sbo, uint32_t mode) {
    return (uint64_t)((addr & 0x3FFFF) >> 4) | ((uint64_t)(lbo >> 4) << 16) | ((uint64_t)(sbo >> 4) << 32) | ((uint64_t)mode << 62);
}

__device__ __forceinline__ void mma16816(float (&c)[4], uint32_t a0, uint32_t a1, uint32_t a2, uint32_t a3, uint32_t b0, uint32_t b1) {
    asm("mma.sync.aligned.m16n8k16.row.col.f32.bf16.bf16.f32 {%0,%1,%2,%3},{%4,%5,%6,%7},{%8,%9},{%0,%1,%2,%3};"
                 : "+f"(c[0]), "+f"(c[1]), "+f"(c[2]), "+f"(c[3]) : "r"(a0), "r"(a1), "r"(a2), "r"(a3), "r"(b0), "r"(b1));
}
__device__ __forceinline__ void mma1688(float (&c)[4], uint32_t a0, uint32_t a1, uint32_t b0) {
    asm("mma.sync.aligned.m16n8k8.row.col.f32.bf16.bf16.f32 {%0,%1,%2,%3},{%4,%5},{%6},{%0,%1,%2,%3};"
                 : "+f"(c[0]), "+f"(c[1]), "+f"(c[2]), "+f"(c[3]) : "r"(a0), "r"(a1), "r"(b0));
}
__device__ __forceinline__ void ldsm_x4(uint32_t& r0, uint32_t& r1, uint32_t& r2, uint32_t& r3, uint32_t a) {
    asm volatile("ldmatrix.sync.aligned.m8n8.x4.shared.b16 {%0,%1,%2,%3}, [%4];" : "=r"(r0), "=r"(r1), "=r"(r2), "=r"(r3) : "r"(a) : "memory");
}
__device__ __forceinline__ void ldsm_x4_t(uint32_t& r0, uint32_t& r1, uint32_t& r2, uint32_t& r3, uint32_t a) {
    asm volatile("ldmatrix.sync.aligned.m8n8.x4.trans.shared.b16 {%0,%1,%2,%3}, [%4];" : "=r"(r0), "=r"(r1), "=r"(r2), "=r"(r3) : "r"(a) : "memory");
}
__device__ __forceinline__ void ldsm_x2(uint32_t& r0, uint32_t& r1, uint32_t a) {
    asm volatile("ldmatrix.sync.aligned.m8n8.x2.shared.b16 {%0,%1}, [%2];" : "=r"(r0), "=r"(r1) : "r"(a) : "memory");
}
__device__ __forceinline__ void ldsm_x2_t(uint32_t& r0, uint32_t& r1, uint32_t a) {
    asm volatile("ldmatrix.sync.aligned.m8n8.x2.trans.shared.b16 {%0,%1}, [%2];" : "=r"(r0), "=r"(r1) : "r"(a) : "memory");
}
__device__ __forceinline__ void stsm_x4(uint32_t a, uint32_t r0, uint32_t r1, uint32_t r2, uint32_t r3) {
    asm volatile("stmatrix.sync.aligned.m8n8.x4.shared.b16 [%0], {%1,%2,%3,%4};" ::"r"(a), "r"(r0), "r"(r1), "r"(r2), "r"(r3) : "memory");
}
__device__ __forceinline__ void stsm_x4_t(uint32_t a, uint32_t r0, uint32_t r1, uint32_t r2, uint32_t r3) {
    asm volatile("stmatrix.sync.aligned.m8n8.x4.trans.shared.b16 [%0], {%1,%2,%3,%4};" ::"r"(a), "r"(r0), "r"(r1), "r"(r2), "r"(r3) : "memory");
}
__device__ __forceinline__ void stsm_x2(uint32_t a, uint32_t r0, uint32_t r1) {
    asm volatile("stmatrix.sync.aligned.m8n8.x2.shared.b16 [%0], {%1,%2};" ::"r"(a), "r"(r0), "r"(r1) : "memory");
}
__device__ __forceinline__ uint32_t movm_t(uint32_t a) {
    uint32_t d;
    asm volatile("movmatrix.sync.aligned.m8n8.trans.b16 %0, %1;" : "=r"(d) : "r"(a));
    return d;
}
__device__ __forceinline__ uint32_t lds32(uint32_t a) { uint32_t v; asm volatile("ld.shared.u32 %0, [%1];" : "=r"(v) : "r"(a) : "memory"); return v; }
__device__ __forceinline__ uint32_t ldsv32(uint32_t a) { uint32_t v; asm volatile("ld.volatile.shared.u32 %0, [%1];" : "=r"(v) : "r"(a) : "memory"); return v; }
__device__ __forceinline__ void sts32(uint32_t a, uint32_t v) { asm volatile("st.shared.u32 [%0], %1;" ::"r"(a), "r"(v) : "memory"); }
__device__ __forceinline__ uint4 lds128(uint32_t a) { uint4 v; asm volatile("ld.shared.v4.u32 {%0,%1,%2,%3}, [%4];" : "=r"(v.x), "=r"(v.y), "=r"(v.z), "=r"(v.w) : "r"(a) : "memory"); return v; }
__device__ __forceinline__ void sts128(uint32_t a, uint4 v) { asm volatile("st.shared.v4.u32 [%0], {%1,%2,%3,%4};" ::"r"(a), "r"(v.x), "r"(v.y), "r"(v.z), "r"(v.w) : "memory"); }

__device__ __forceinline__ void stg128(void* p, uint4 v) { asm volatile("st.global.v4.u32 [%0], {%1,%2,%3,%4};" ::"l"(p), "r"(v.x), "r"(v.y), "r"(v.z), "r"(v.w) : "memory"); }

__device__ __forceinline__ uint4 ldg128(const void* p) { uint4 v; asm volatile("ld.global.v4.u32 {%0,%1,%2,%3}, [%4];" : "=r"(v.x), "=r"(v.y), "=r"(v.z), "=r"(v.w) : "l"(p) : "memory"); return v; }
__device__ __forceinline__ uint2 ldg64(const void* p) { uint2 v; asm volatile("ld.global.v2.u32 {%0,%1}, [%2];" : "=r"(v.x), "=r"(v.y) : "l"(p) : "memory"); return v; }
__device__ __forceinline__ uint32_t ldg32(const void* p) { uint32_t v; asm volatile("ld.global.u32 %0, [%1];" : "=r"(v) : "l"(p) : "memory"); return v; }

__device__ __forceinline__ uint32_t pack2(float lo, float hi) {
    uint32_t r;
    asm("cvt.rn.bf16x2.f32 %0, %1, %2;" : "=r"(r) : "f"(hi), "f"(lo));
    return r;
}
__device__ __forceinline__ float bf_lo(uint32_t v) { return __uint_as_float(v << 16); }
__device__ __forceinline__ float bf_hi(uint32_t v) { return __uint_as_float(v & 0xFFFF0000u); }
__device__ __forceinline__ float rbf(float x) { return __uint_as_float(pack2(0.f, x) & 0xFFFF0000u); }
__device__ __forceinline__ float ex2(float x) { float r; asm("ex2.approx.ftz.f32 %0, %1;" : "=f"(r) : "f"(x)); return r; }

__device__ __forceinline__ float2 ln_finish(float sum, float sumsq) {
    const float m = sum * (1.0f / DM);
    const float v = fmaxf(fmaf(sumsq, 1.0f / DM, -m * m), 0.f);
    float s, r;
    asm("sqrt.approx.ftz.f32 %0, %1;" : "=f"(s) : "f"(rbf(rbf(v) + 1e-5f)));
    asm("rcp.approx.ftz.f32 %0, %1;" : "=f"(r) : "f"(rbf(s)));
    return make_float2(m, r);
}
__device__ __forceinline__ uint32_t ln_finish_packed(float sum, float sumsq) {
    const float m = sum * (1.0f / DM);
    const float v = fmaxf(fmaf(sumsq, 1.0f / DM, -m * m), 0.f);
    float s;
    asm("sqrt.approx.ftz.f32 %0, %1;" : "=f"(s) : "f"(rbf(rbf(v) + 1e-5f)));
    return pack2(s, m);
}
__device__ __forceinline__ float frsq(float x) { float r; asm("rsqrt.approx.ftz.f32 %0, %1;" : "=f"(r) : "f"(x)); return r; }
__device__ __forceinline__ float frcp(float x) { float r; asm("rcp.approx.ftz.f32 %0, %1;" : "=f"(r) : "f"(x)); return r; }
__device__ __forceinline__ bool elect_one() {
    uint32_t p;
    asm volatile("{\n.reg .pred p;\nelect.sync _|p, 0xffffffff;\nselp.u32 %0, 1, 0, p;\n}" : "=r"(p));
    return p != 0;
}
__device__ __forceinline__ void cluster_arrive_relaxed() { asm volatile("barrier.cluster.arrive.relaxed.aligned;" ::: "memory"); }
__device__ __forceinline__ void cluster_wait() { asm volatile("barrier.cluster.wait.aligned;" ::: "memory"); }
__device__ __forceinline__ unsigned long long ld_ll(const unsigned long long* p) {
    unsigned long long v;
    asm volatile("ld.relaxed.gpu.global.b64 %0, [%1];" : "=l"(v) : "l"(p) : "memory");
    return v;
}
__device__ __forceinline__ void st_ll(unsigned long long* p, uint32_t payload, uint32_t tag) {
    const unsigned long long v = (unsigned long long)payload | ((unsigned long long)tag << 32);
    asm volatile("st.relaxed.gpu.global.b64 [%0], %1;" ::"l"(p), "l"(v) : "memory");
}
__device__ __forceinline__ uint4 ld_ll4(const uint4* p) {
    uint4 v;
    asm volatile("{\n.reg .b128 t;\n.reg .b64 a, b;\nld.relaxed.gpu.global.b128 t, [%4];\nmov.b128 {a, b}, t;\nmov.b64 {%0, %1}, a;\nmov.b64 {%2, %3}, b;\n}"
                 : "=r"(v.x), "=r"(v.y), "=r"(v.z), "=r"(v.w) : "l"(p) : "memory");
    return v;
}
__device__ __forceinline__ void st_ll4(uint4* p, uint32_t x, uint32_t y, uint32_t z, uint32_t w) {
    asm volatile("{\n.reg .b128 t;\n.reg .b64 a, b;\nmov.b64 a, {%1, %2};\nmov.b64 b, {%3, %4};\nmov.b128 t, {a, b};\nst.relaxed.gpu.global.b128 [%0], t;\n}"
                 ::"l"(p), "r"(x), "r"(y), "r"(z), "r"(w) : "memory");
}

__device__ __forceinline__ void bulk_s2g(void* dst, uint32_t src, uint32_t bytes) {
    asm volatile("cp.async.bulk.global.shared::cta.bulk_group [%0], [%1], %2;" ::"l"(dst), "r"(src), "r"(bytes) : "memory");
}
__device__ __forceinline__ void bulk_commit() { asm volatile("cp.async.bulk.commit_group;" ::: "memory"); }
__device__ __forceinline__ void bulk_wait() { asm volatile("cp.async.bulk.wait_group 0;" ::: "memory"); }
__device__ __forceinline__ void fence_async_global() { asm volatile("fence.proxy.async.global;" ::: "memory"); }
__device__ __forceinline__ void fence_release() { asm volatile("fence.release.gpu;" ::: "memory"); }
__device__ __forceinline__ void fence_acquire() { asm volatile("fence.acquire.gpu;" ::: "memory"); }
template<int TA, int TB>
__device__ __forceinline__ void wgmma_n192(float (&d)[96], uint64_t da, uint64_t db, int scale_d) {
  asm volatile("{\n.reg .pred p;\nsetp.ne.b32 p, %98, 0;\n"
    "wgmma.mma_async.sync.aligned.m64n192k16.f32.bf16.bf16 "
    "{%0, %1, %2, %3, %4, %5, %6, %7, %8, %9, %10, %11, %12, %13, %14, %15, %16, %17, %18, %19, %20, %21, %22, %23, %24, %25, %26, %27, %28, %29, %30, %31, %32, %33, %34, %35, %36, %37, %38, %39, %40, %41, %42, %43, %44, %45, %46, %47, %48, %49, %50, %51, %52, %53, %54, %55, %56, %57, %58, %59, %60, %61, %62, %63, %64, %65, %66, %67, %68, %69, %70, %71, %72, %73, %74, %75, %76, %77, %78, %79, %80, %81, %82, %83, %84, %85, %86, %87, %88, %89, %90, %91, %92, %93, %94, %95}, %96, %97, p, 1, 1, %99, %100;\n}\n"
    : "+f"(d[0]), "+f"(d[1]), "+f"(d[2]), "+f"(d[3]), "+f"(d[4]), "+f"(d[5]), "+f"(d[6]), "+f"(d[7]), "+f"(d[8]), "+f"(d[9]), "+f"(d[10]), "+f"(d[11]), "+f"(d[12]), "+f"(d[13]), "+f"(d[14]), "+f"(d[15]), "+f"(d[16]), "+f"(d[17]), "+f"(d[18]), "+f"(d[19]), "+f"(d[20]), "+f"(d[21]), "+f"(d[22]), "+f"(d[23]), "+f"(d[24]), "+f"(d[25]), "+f"(d[26]), "+f"(d[27]), "+f"(d[28]), "+f"(d[29]), "+f"(d[30]), "+f"(d[31]), "+f"(d[32]), "+f"(d[33]), "+f"(d[34]), "+f"(d[35]), "+f"(d[36]), "+f"(d[37]), "+f"(d[38]), "+f"(d[39]), "+f"(d[40]), "+f"(d[41]), "+f"(d[42]), "+f"(d[43]), "+f"(d[44]), "+f"(d[45]), "+f"(d[46]), "+f"(d[47]), "+f"(d[48]), "+f"(d[49]), "+f"(d[50]), "+f"(d[51]), "+f"(d[52]), "+f"(d[53]), "+f"(d[54]), "+f"(d[55]), "+f"(d[56]), "+f"(d[57]), "+f"(d[58]), "+f"(d[59]), "+f"(d[60]), "+f"(d[61]), "+f"(d[62]), "+f"(d[63]), "+f"(d[64]), "+f"(d[65]), "+f"(d[66]), "+f"(d[67]), "+f"(d[68]), "+f"(d[69]), "+f"(d[70]), "+f"(d[71]), "+f"(d[72]), "+f"(d[73]), "+f"(d[74]), "+f"(d[75]), "+f"(d[76]), "+f"(d[77]), "+f"(d[78]), "+f"(d[79]), "+f"(d[80]), "+f"(d[81]), "+f"(d[82]), "+f"(d[83]), "+f"(d[84]), "+f"(d[85]), "+f"(d[86]), "+f"(d[87]), "+f"(d[88]), "+f"(d[89]), "+f"(d[90]), "+f"(d[91]), "+f"(d[92]), "+f"(d[93]), "+f"(d[94]), "+f"(d[95])
    : "l"(da), "l"(db), "r"(scale_d), "n"(TA), "n"(TB));
}

template<int TA, int TB>
__device__ __forceinline__ void wgmma_n48(float (&d)[24], uint64_t da, uint64_t db, int scale_d) {
  asm volatile("{\n.reg .pred p;\nsetp.ne.b32 p, %26, 0;\n"
    "wgmma.mma_async.sync.aligned.m64n48k16.f32.bf16.bf16 "
    "{%0, %1, %2, %3, %4, %5, %6, %7, %8, %9, %10, %11, %12, %13, %14, %15, %16, %17, %18, %19, %20, %21, %22, %23}, %24, %25, p, 1, 1, %27, %28;\n}\n"
    : "+f"(d[0]), "+f"(d[1]), "+f"(d[2]), "+f"(d[3]), "+f"(d[4]), "+f"(d[5]), "+f"(d[6]), "+f"(d[7]), "+f"(d[8]), "+f"(d[9]), "+f"(d[10]), "+f"(d[11]), "+f"(d[12]), "+f"(d[13]), "+f"(d[14]), "+f"(d[15]), "+f"(d[16]), "+f"(d[17]), "+f"(d[18]), "+f"(d[19]), "+f"(d[20]), "+f"(d[21]), "+f"(d[22]), "+f"(d[23])
    : "l"(da), "l"(db), "r"(scale_d), "n"(TA), "n"(TB));
}

__device__ __forceinline__ void wgmma_rs80(float (&d)[40], const uint4& a, uint64_t db, int scale_d) {
  asm volatile("{\n.reg .pred p;\nsetp.ne.b32 p, %45, 0;\n"
    "wgmma.mma_async.sync.aligned.m64n80k16.f32.bf16.bf16 {%0,%1,%2,%3,%4,%5,%6,%7,%8,%9,%10,%11,%12,%13,%14,%15,%16,%17,%18,%19,%20,%21,%22,%23,%24,%25,%26,%27,%28,%29,%30,%31,%32,%33,%34,%35,%36,%37,%38,%39}, {%40,%41,%42,%43}, %44, p, 1, 1, 1;\n}\n"
    : "+f"(d[0]), "+f"(d[1]), "+f"(d[2]), "+f"(d[3]), "+f"(d[4]), "+f"(d[5]), "+f"(d[6]), "+f"(d[7]), "+f"(d[8]), "+f"(d[9]), "+f"(d[10]), "+f"(d[11]), "+f"(d[12]), "+f"(d[13]), "+f"(d[14]), "+f"(d[15]), "+f"(d[16]), "+f"(d[17]), "+f"(d[18]), "+f"(d[19]), "+f"(d[20]), "+f"(d[21]), "+f"(d[22]), "+f"(d[23]), "+f"(d[24]), "+f"(d[25]), "+f"(d[26]), "+f"(d[27]), "+f"(d[28]), "+f"(d[29]), "+f"(d[30]), "+f"(d[31]), "+f"(d[32]), "+f"(d[33]), "+f"(d[34]), "+f"(d[35]), "+f"(d[36]), "+f"(d[37]), "+f"(d[38]), "+f"(d[39])
    : "r"(a.x), "r"(a.y), "r"(a.z), "r"(a.w), "l"(db), "r"(scale_d));
}

__device__ const __align__(1024) uint32_t c_fft[11264] = {
0x2ddc2dba,0x2fe62eb5,0x2ed02eb5,0xafffaf6e,0x2e1f2dfe,0x2e3f2fbc,0x2f022ee9,0xad27af30,0x2e5e2e3f,0x1fd92b5e,0x2f302f1a,0x244ea875,0x2e992e7c,0xad96a993,0x2f5a2f46,0x2e992c32,
0xad00ad72,0xa17eac32,0xa17ea515,0xabb79cb6,0xac07ac87,0x2dfe29f1,0x1fd99648,0xafedae99,0xa9f1ab05,0x2fd42fbc,0x26a1244e,0xad96af91,0xa765a8d5,0x2aaa2e3f,0x29932875,0x2515a8d5,
0xae99adfe,0xb000aee9,0xaf6eafbc,0x2c872f30,0xaf80af1a,0xac32af02,0xae7caf02,0xaaaa217e,0xaff4afc9,0x2b5e9cb6,0xad27addc,0xaff4ae7c,0xafedb000,0x2ffc2eb5,0xab05ac5d,0xacd8af5a,
0x2c072d27,0x9fd92bb7,0xadfead00,0x2fed2e1f,0x25db2993,0xaf6eacb0,0xaf6eaed0,0x2c5d2f46,0xa5151648,0xaddcafdd,0xafffafd4,0xac321648,0xabb7a934,0x28d5a814,0xafa0afed,0xaff4af30,
0x2f302e3f,0x2fed2f1a,0x28142b5e,0x2934a875,0x30002fc9,0x26a12ddc,0xa5db1cb6,0x30002e7c,0x2f462fd4,0xaed0aa4e,0xacb0aa4e,0x29932e99,0x2d272e5e,0xae3faffc,0xaf02adfe,0xae1fa814,
0xa9f1acd8,0x26a1ab05,0x2fd42ffc,0xad96afed,0x2515a30e,0x2fff2e1f,0x2ddc2f1a,0x2c32a30e,0x2d272aaa,0x28752e7c,0x28752c32,0x2fa02f80,0x2f912e99,0xaee9a9f1,0xa8141648,0x9fd92c87,
0xafa0ae7c,0xafafaf46,0x2d002993,0xafa0ac32,0xaf91b000,0x244eac5d,0x2fbc2eb5,0xab05af5a,0xac87ae5e,0x30002dfe,0x2f6e2ffc,0x2e992814,0x1cb6a875,0x25152e1f,0x2c322e1f,0x2d722ff4,
0x27652c87,0xa9932a4e,0xaaaaadba,0xa5152c87,0xabb7a44e,0xafa0af30,0x28d59fd9,0xaff4ae5e,0xaf91ae1f,0x2814abb7,0x2ee92d00,0x1fd9ad27,0xaf5aafff,0x2fd42ed0,0x2fd42fe6,0x30002ddc,
0x2f462f6e,0x2c322fdd,0x2e7c2fdd,0xa993b000,0xab5e2934,0xafafacd8,0xad00244e,0x2f1a2dfe,0xaee9afaf,0x2f30a17e,0xadfeaff8,0xafbca30e,0x2c5da765,0xa9f12ddc,0x2d969cb6,0x2c5dacb0,
0x2bb7a993,0x2f1aa515,0x2f1a2765,0xaff4aaaa,0x2e5e2fd4,0xab052dba,0x29342f6e,0x2ee9a6a1,0xadba1fd9,0xa5dbafed,0xafddac07,0xaa4e2dfe,0xacb0aff8,0x2ddc2f02,0x9cb6ae3f,0xa765aff8,
0xaeb5af91,0xaa4eafed,0x9648ae5e,0xac5d2d4d,0x2ddca17e,0x2e7c2e3f,0x2fc92e3f,0x1cb6afa0,0x2bb72fe6,0xaff8a993,0xab5e2aaa,0x2bb72fc9,0xafbcaa4e,0x2f30a5db,0xadfeafdd,0xaee9adba,
0xacd828d5,0xaf91230e,0xaf30af02,0x2c072fa0,0xac5dafff,0x2dbaac32,0x2dbaa515,0xae99addc,0x2fc929f1,0xa9932eb5,0x2aaa2fdd,0x2fe629f1,0xa30e2dfe,0xa17eafed,0xaff8ac07,0xafaf1fd9,
0x2dfe2faf,0x28142ff8,0xae5e217e,0x2ffc230e,0xaf5aa515,0xac87af46,0xa6a1af80,0xaf5a2765,0x1cb6ae99,0x2e7c2dba,0x2fc92dba,0x2ddcac5d,0x2f1a2ee9,0xafafab05,0xad002934,0xab5e2e5e,
0x2dbaa814,0x2fdd9fd9,0x25db2f91,0x2a4eaee9,0x27652faf,0xaf4628d5,0xaf80ae1f,0xa5152faf,0xafa0addc,0x2e3fac32,0x2e3fa515,0xa17eafff,0x2dfea6a1,0xacd82dba,0x244e2f6e,0x29342fd4,
0xad27afc9,0xa30eafff,0x2faf2d72,0xad27ae7c,0x2ffc2a4e,0x28142fdd,0xae5e25db,0x2dfe2dba,0xac5d2c07,0xaa4eaf91,0x9648af30,0xaeb5acd8,0xa993aff4,0x2c322f1a,0x2e7c2f1a,0x2f462bb7,
0xae7c26a1,0xafff1648,0x2d72aa4e,0xafc926a1,0x230eaee9,0x2ff89fd9,0x217e2f91,0x2fafa814,0x2d4d2fa0,0xafed230e,0xae5eaf02,0xaf9128d5,0xb000aaaa,0x2fdda515,0x2fdd2765,0x2f6ea993,
0x9cb63000,0xacb02fd4,0xa7652fd4,0x2ddcaf5a,0x217eaffc,0x2ff4ac07,0x2875afbc,0xaff82934,0xa44e2ff4,0xadfea8d5,0xa9342fa0,0x2cd82bb7,0x25dbafe6,0x16482f46,0x29f1af80,0x25dbafc9,
0x2ff41cb6,0x2e1f2765,0x2e1f2cb0,0xa875addc,0xafbca5db,0x1fd9af5a,0xad4dad96,0xacd82fdd,0x2f5a2934,0xaeb52ee9,0x2c5d2e5e,0x3000ab05,0xaed0ab5e,0x2f80a30e,0xaaaaaf02,0xacb0ab5e,
0x25dbaffc,0x2d96afbc,0x2f5aac07,0xafdd2934,0xaaaa2fa0,0xafc92875,0xafe62875,0x29932d27,0x2d00aed0,0x28d52d72,0x2ff89cb6,0x2d00afe6,0xae5e2d96,0x2d4dafd4,0xaf91a6a1,0xafed29f1,
0xafbca17e,0xad4da875,0x1fd9aff4,0xacd82ff8,0x2e992aaa,0xaa4e2fe6,0xaa4e2fc9,0x2fd4a993,0xacb0ad96,0x2fffac87,0x2d72aeb5,0xa765ad96,0x28752f30,0xab5eac07,0xaf1a2cd8,0xae3f2f91,
0xa9342ff4,0xae5e2fa0,0xaee9a8d5,0x2b052bb7,0x2d96aed0,0x2eb59cb6,0x2c872d72,0x2d96afe6,0xaf802c5d,0x2765af6e,0xa515af6e,0xaf4625db,0x2ff8a44e,0xaff42d4d,0xa8752ffc,0xa17e2ee9,
0x2f5a244e,0x2c5d2934,0xaeb52dfe,0x3000acd8,0xacb0ad00,0x2d72aff8,0x2fffa8d5,0xa765ad00,0x217e2f80,0xaf022515,0xaf02a765,0xaf1a2f46,0x2b05afdd,0xa8142f5a,0x2c072d96,0x2d4d25db,
0x2b5eafe6,0x2f02af80,0x230e2f46,0x2b5eafc9,0xaf302d96,0xacd8a6a1,0x2c07afd4,0xaf9129f1,0x2fdda44e,0xad962ffc,0xaf5a2d4d,0xa5db2ee9,0xad72abb7,0x2e7ca17e,0x2fc9a17e,0x2fffad00,
0xaed0a5db,0xaaaaa9f1,0x2f809648,0xacb0a5db,0x28752e5e,0xaf1a2f91,0xab5ead4d,0xae3f2fed,0x2b05aff8,0x2c072875,0xa8142ff4,0x2d4d217e,0xaf6e2d72,0x2eb5afc9,0x2eb5ae7c,0x2dbaafff,
0xaf802f5a,0xafc92e99,0xafe62e99,0x2f46ad96,0x28d52b05,0xaf022fed,0x230e2cd8,0x2fa0affc,0x2fbcaf02,0xa9342d27,0x2ffcae1f,0x2c07ae3f,0xa6a1ac32,0x2a4e9cb6,0x9648ad72,0xa6a1a515,
0x28752aaa,0xa8d52cb0,0xa8d52ed0,0x2e3faf80,0x2fedaeb5,0x29349648,0x2f30aa4e,0x2814ac5d,0x1648ad4d,0x2e99acd8,0x2c87afbc,0xa9f11fd9,0xafe62d27,0x2fffafaf,0xaddc230e,0xaed02d27,
0x2fd4af30,0x2f6eae5e,0x2dbaa44e,0xa6a19fd9,0x1cb6ad27,0x2fe6aff4,0x2ed0aff4,0xad722b5e,0xafaf2cb0,0x2e1faf46,0xa8d5a993,0xafaf2ed0,0xac072f6e,0x2934ac87,0xaffc2e99,0xafbc3000,
0xa44eab5e,0x2b05ad00,0x2f91afaf,0xafbc2f1a,0xafd42d72,0x1648a765,0x1648acb0,0xafdd2fff,0xac322f5a,0xaaaa26a1,0xaf802c87,0xae7c2f5a,0x2d009fd9,0xae1f2cd8,0xad272fbc,0xabb72d4d,
0xaffc2f02,0xaee92e1f,0x244ead27,0xad4d2e3f,0xa9f12e7c,0xafdd2f80,0xaeb52aaa,0xa9f12c32,0x2d72a5db,0xafe63000,0xaed03000,0x9cb626a1,0x2fa0afbc,0xaf022f91,0x230e2b05,0x28d5a44e,
0x96482c07,0xac872d4d,0xae992b05,0x29f1a814,0x2ed0abb7,0xa9932b5e,0xaf462ff8,0x2cb0abb7,0x2f1aafff,0xa30e2765,0xa30e2cb0,0x2e1fad72,0x1fd9ac5d,0x244e9648,0x2e5eaa4e,0x2f30aeb5,
0x2ff8aed0,0x2e3faddc,0xaf022fff,0x2ff8afe6,0x2d4daf6e,0x2ee9ae99,0xa44e2c87,0x2ffcb000,0xa6a1a814,0x2f6eaf30,0x2dbaa934,0x2fd4afed,0xaf462d00,0x2fc9afa0,0x2fe6afa0,0x2f80afaf,
0x2515ac5d,0x2d72ad96,0x1cb629f1,0x2c32ac5d,0xad002814,0x2d27ad4d,0x2e1fab05,0x2bb7ac07,0xaffc2f1a,0x2cd8ad00,0x2fedafaf,0x2b05ab5e,0xadba2f80,0x2c87acb0,0x2c87aed0,0x2a4eaaaa,
0x2f802f6e,0x2fc92fdd,0x2fe62fdd,0xaf46b000,0x2fa02f91,0x2bb72e5e,0x2ff42fed,0xa8d5ad4d,0x2fbc2faf,0xa934217e,0x2ffc2ff8,0x2c07230e,0x2fd42fc9,0xaf5aad72,0x30002fff,0x2fd42e7c,
0x2bb72aaa,0x2f1a2cb0,0x2f1a2ed0,0xaff4af80,0x2cd82c5d,0x2f303000,0x2f912f5a,0xac07aeb5,0x2dba2d4d,0x25db2cd8,0x2fdd2fbc,0x2a4e9fd9,0x2e7c2e1f,0xad72a875,0x2fff2ff4,0x2fc92e1f,
0xa6a1a934,0x29f1a44e,0x2d962cd8,0xafd4adfe,0x1cb6a17e,0x2fe62e3f,0x2ed02e3f,0xad72afa0,0x28752515,0x2d272f80,0x2fa02f46,0x2875a765,0x2c072a4e,0xa93425db,0x2ffc2fdd,0x2fbc2dba,
0xae5eaf1a,0xa934ae3f,0x2b052875,0xaee9ab5e,0xac5dad72,0x2dba2765,0x2dba2cb0,0xae99afff,0xa765aa4e,0x2f802fd4,0x2f462e99,0x2515aa4e,0x230e9fd9,0x217e2cd8,0x2ff82fbc,0x2faf2d4d,
0xaffcafaf,0xaee9aff8,0x244ea17e,0xad4da30e,0xaf6eafe6,0x25dbaaaa,0x2c5d2993,0xaf6eafc9,0xad72ae99,0x2fe62dba,0x2ed02dba,0x1cb6ac5d,0xa8d5ac07,0x2bb72f30,0x2ff42f91,0x2fa02cd8,
0xadbaac07,0xafddad4d,0xa5dbab05,0xaa4e2814,0xafc9af02,0xaaaaaf1a,0x2993217e,0xafe6af02,0xafa0afff,0x2e3f2765,0x2e3f2cb0,0xa17ead72,0xad4daeb5,0x2e5e3000,0x2fed2f5a,0x2f912c5d,
0xa17e2765,0xad001cb6,0xabb7addc,0xa17e2cb0,0xad4daa4e,0xaee9afdd,0x244ea5db,0xaffcadba,0xafd4aee9,0x29f1a934,0x2d962b05,0xa6a1ae5e,0xaf46aff4,0x2fc92f1a,0x2fe62f1a,0x2f802bb7,
0x2cb02eb5,0x1cb62dba,0xaddcaf6e,0x27652eb5,0xa30e2814,0xaff8ad4d,0xa17eab05,0xafafac07,0xadfeab5e,0xa44eae3f,0x2cd82875,0xa934af1a,0xb000af80,0x2fdd2cb0,0x2fdd2ed0,0x2f6e2aaa,
0x2d723000,0x25152fd4,0x2c322fd4,0x1cb6af5a,0xae1f9fd9,0xae3faee9,0xaf02a814,0x2d272f91,0xacd8aff4,0x2ffc28d5,0xab05afa0,0xafedabb7,0x2e992515,0xad962aaa,0x2f5a2993,0x2e99a765,
0x2ff42ddc,0x2e1f2ed0,0x2e1f2fe6,0xa875afff,0xa8142c87,0xaffca9f1,0xadfe1648,0x2e5e2e99,0xaf5aaf30,0x2eb5a814,0xac5dafed,0xb000a934,0x2c32a8d5,0xa9932e3f,0x2f462875,0x2e7ca8d5,
0x2e991fd9,0x30002814,0x2f6e2ee9,0xac87af91,0x29932fa0,0xaed02875,0xacb02875,0x2f462d27,0xaff4ac32,0x2b5eaddc,0xad27afff,0xaff4a515,0x244ead96,0x1fd92fd4,0x2f3026a1,0x2e5ea9f1,
0x2814ad27,0x2dfeabb7,0x2ffc2d00,0xae5eae1f,0x2e992f80,0xaa4e2e7c,0xaa4e2c32,0x2fd42aaa,0xae7c1648,0x9cb6afdd,0xaddcafd4,0xafc91648,0xa875af91,0x2b5e2fbc,0x2f1a244e,0x2e3fab05,
0xab05aff4,0x244eafa0,0x2fbc28d5,0xaf91abb7,0x30002c32,0x26a12fff,0xa5db2ddc,0x30002515,0xaaaa2c5d,0xac32af6e,0xae7caf6e,0xaf8025db,0xad27afed,0x2e3f2dfe,0x2f021fd9,0x2e1fac07,
0xaf5aae5e,0xac5daf30,0x2eb59fd9,0xb000a44e,0x2e7ca30e,0x2ddc2e1f,0x1cb62f1a,0x2fc9a30e,0x217e2f46,0xaf02acb0,0xaf02aed0,0xaf1a2993,0xaf30ae99,0x2fbc29f1,0x2ee99648,0x2dfeac87,
0xafa0a515,0xafafa993,0x2d00aaaa,0xafa02765,0x2934ad96,0x2fed26a1,0x28142fd4,0x2f30a9f1,0x2c872fed,0xb0009fd9,0xaf6eadfe,0xae992c07,0xafffabb7,0x2fe6a17e,0x2ed0a17e,0x2ddcad00,
0xac322c87,0xaf462a4e,0x2993adba,0xae7c2c87,0xa875afed,0x2f1aab05,0x2b5e2ffc,0x2e3facd8,0x2f302e1f,0xaee92bb7,0xafbcad00,0xadfe2d27,0xaf6e9cb6,0x2eb5ac32,0x2eb5a515,0x2dbaad72,
0xaaaa2f5a,0xaed02e99,0xacb02e99,0x2f80ad96,0x2b5eaf30,0x2fafa44e,0x2d00ae5e,0xaf1a9fd9,0xac072f02,0xab05ad27,0xad4d2e1f,0x28142e3f,0x2c5daed0,0xa9f12fff,0x2d96addc,0x2c5dafe6,
0x28752f80,0xa8d52fe6,0xa8d52fc9,0x2e3faf46,0xa44eafd4,0x2f91adba,0x2b05af6e,0xafbc26a1,0x96482ffc,0xae99a44e,0xac872ee9,0x29f12d4d,0x2515aff8,0x1cb62f02,0x2d72ae3f,0x2c32aff8,
0x2eb52b05,0x2a4e2cd8,0x16482fed,0x2c5daffc,0xad72ad27,0x2cb0aff4,0x2765aff4,0xafff2b5e,0x2bb72e7c,0xaff82aaa,0xab5e2f80,0x2bb72c32,0xa814af6e,0x2b052c87,0x2d4dae99,0x2c07b000,
0x2feda8d5,0x2f30a30e,0x29342f02,0x2814afa0,0xafd49cb6,0x1648aed0,0x1648afe6,0xafdd2d72,0x2ed029f1,0xaf462eb5,0xa9932fdd,0x2cb029f1,0xad00ad4d,0x2e1f244e,0x2d27aee9,0x2bb7affc,
0x2d4daf02,0x2fbcae1f,0x2cd82d27,0x9fd9ae3f,0xaf5a2cb0,0xac87a993,0xa6a1af46,0xaf5a2ed0,0x2fffa5db,0xacb03000,0xa7653000,0x2d7226a1,0xaf1aa814,0x2fafa934,0x2d00af30,0x2b5eafed,
0x1648afbc,0x2c87affc,0x2e992934,0xa9f1ac07,0xac322faf,0xaf8028d5,0xaaaaae1f,0xae7c2faf,0x2f1aad72,0xa30e2ed0,0xa30e2fe6,0x2e1f1cb6,0xaffc26a1,0x2fedadba,0x2cd8af6e,0x2b05afd4,
0xad27ac32,0xa30ead72,0x2faf9cb6,0xad27a515,0x1fd92f6e,0xafbc2e99,0xacd8ac87,0xad4d3000,0x2c5dafbc,0x2a4e2b05,0x16482f91,0x2eb5a44e,0xaf802d00,0x2ed0afa0,0x2cb0afa0,0x2aaaafaf,
0xafe626a1,0xaddc1648,0x2fffaa4e,0xaed026a1,0x2d002c07,0xad272ffc,0xae1fa934,0xabb72fbc,0x1fd9afa0,0x2e5ea30e,0x244e2f02,0x2f30a8d5,0xadba2f46,0x2c87afe6,0x2c87afc9,0x2a4eaf80,
0xafff2d96,0xae7c2c5d,0xafc92c5d,0x2d72a9f1,0xa17e2dfe,0xaff42fbc,0xa8752ee9,0x2ff8af30,0x2fedad00,0xad4d2f1a,0x2f91ab5e,0x2e5eafaf,0x25dbae7c,0x16482993,0x29f1af46,0x25dbac32,
0xae3f2fff,0xaff82fc9,0xaff82e7c,0x2f02ad72,0x2c0725db,0xadfe2f5a,0x9fd92d96,0x2fedafdd,0x2f6eaf91,0xa6a12c07,0x2fd4acd8,0x2dbaaf30,0xa765ab5e,0x2aaaa30e,0x2993af02,0x2515ab5e,
0xa5db2dfe,0xad962ee9,0xaf5a2fbc,0x2fddaf30,0x2f46ab5e,0xa7652bb7,0x25152bb7,0x2f80aff8,0x2d00afc9,0x28d59cb6,0x2ff8addc,0x2d00ae7c,0xacd89648,0x2dfeac5d,0x2934aeb5,0x244eaa4e,
0x2c07217e,0x9fd92875,0xadfe2ff4,0x2fedaff8,0x2fddaf46,0x29f1a515,0x29f12765,0x2eb5af80,0x2515ad96,0x2ddcac87,0x2fffaeb5,0x2c32ad96,0xaf022b05,0x2fa0aee9,0x28d5ae5e,0x230ea934,
0x2f91ad00,0x2cd8ab5e,0xac072f1a,0x2f30afaf,0x2d96afc9,0x2eb5addc,0x2c879cb6,0x2d96ae7c,0xa993a6a1,0x2fc9af5a,0x2fe6af5a,0x2aaaac87,0xaff82e5e,0x2ff4affc,0x2875adfe,0x217ea814,
0x2f6eafed,0x2fd4af91,0xa6a12d4d,0x2dbaae5e,0x2515ad00,0x2fffaff8,0x2ddca8d5,0x2c32ad00,0xae1f2993,0x2fafafe6,0x2fafafc9,0x28d5aaaa,0xaf912fdd,0x2ee9af5a,0x2814ad96,0x1fd9a5db,
0x2b5eae7c,0x2f02af46,0x230e2993,0x2b5eac32,0xab059648,0x2e5eaeb5,0x2ee9ac5d,0x2934aa4e,0xafdd2e5e,0x2d96adfe,0x2f5aaffc,0x25dba814,0xaddc2faf,0x2cb0ad27,0x2765ad27,0x1cb6a30e,
0xa765a5db,0x2993a9f1,0x2aaa9648,0x2515a5db,0xaf022cd8,0x28d5a934,0x2fa0adfe,0x230ea44e,0xaf912ff8,0x2814a875,0x2ee9aff4,0x1fd9a17e,0xaa4e2ddc,0x26a1a765,0x26a1acb0,0x16489cb6,
0x2d722d96,0x25152c5d,0x2c322c5d,0x1cb6a9f1,0x2d272d4d,0xad00a814,0x2bb72c07,0x2e1f2b05,0x2cd82d00,0xaffcaf1a,0x2b052b5e,0x2fed2faf,0x2c872cb0,0xadbaaf80,0x2a4e2aaa,0x2c872ed0,
0x2e3f2ddc,0x2ff82ed0,0x2ff82fe6,0xaf02afff,0x2ee92e99,0x2d4d2f6e,0x2ffc3000,0xa44eac87,0x2f6e2f30,0xa6a12814,0x2fd42fed,0x2dba2934,0x2fc92fa0,0xaf46ad00,0x2f802faf,0x2fe62fa0,
0xac87ad4d,0x9648ac07,0x29f12814,0xae99ab05,0xa993ab5e,0x2ed02bb7,0x2cb02bb7,0xaf46aff8,0xa30ea765,0x2f1a2fff,0x2e1f2d72,0xa30eacb0,0x244e1648,0x1fd92c5d,0x2f302eb5,0x2e5e2a4e,
0xaee9ae1f,0xaffcaf02,0xad4dae3f,0x244e2d27,0xafddaf80,0xa9f1ae7c,0xa9f1ac32,0xaeb5aaaa,0xafe6b000,0x2d7225db,0x9cb6a6a1,0xaed0b000,0xaf02af91,0x2fa02fbc,0x28d5244e,0x230eab05,
0x2b052d00,0xa44e2b5e,0xafbcaf1a,0x2f912faf,0x16482765,0xafd4ad72,0xafddafff,0x16482cb0,0xaaaaa6a1,0xac32af5a,0xae7caf5a,0xaf80ac87,0xae1facd8,0x2d001fd9,0xabb7ad4d,0xad27afbc,
0x2f6e2e5e,0x2fd42f30,0xa6a11fd9,0x2dba244e,0x2fe62ff4,0x1cb62d27,0xad72ab5e,0x2ed02ff4,0x2e1f2f46,0xafafacb0,0xafafaed0,0xa8d52993,0x29342c87,0xac07af6e,0xafbcb000,0xaffcae99,
0xa8d5acb0,0x2875aaaa,0x2e3f2f80,0xa8d5aed0,0x29341648,0x2fed2eb5,0x28142c5d,0x2f302a4e,0x2e992cd8,0x16482d4d,0xa9f19fd9,0x2c872fbc,0x2fff2faf,0xafe6ad27,0xaed0ad27,0xaddca30e,
0xafc9ae99,0xaf80af5a,0x2f462d96,0xafe6ae99,0xaf02afed,0x28d5ab05,0x2fa02ffc,0x230eacd8,0xa934ad27,0x2fbc2f02,0x2c072e3f,0x2ffc2e1f,0x2a4e1cb6,0xa6a12c32,0xa6a12515,0x96482d72,
0xaaaa29f1,0xaed025db,0xacb025db,0x2f801648,0xaf1aaf91,0x2875ae5e,0xae3fafed,0xab5e2d4d,0x2c07a875,0x2b052ff8,0x2d4da17e,0xa814aff4,0x2eb52fc9,0xaf6ead72,0x2dba2fff,0x2eb52e7c,
0x2f022f80,0x2b5e2fe6,0x2b5e2fc9,0x230eaf46,0xacd826a1,0xaf30ad96,0xaf91a9f1,0x2c072fd4,0xad96affc,0x2fdd244e,0xa5dbaee9,0xaf5aad4d,0x2e7c217e,0xad722bb7,0x2fff2d00,0x2fc9217e,
0x2c5da934,0x2f5aa44e,0x30002cd8,0xaeb5adfe,0x2d722ff8,0xacb02d00,0xa7652d00,0x2fff28d5,0xaf02a515,0x217eaf80,0xaf1aaf46,0xaf022765,0xa814af5a,0x2b052fdd,0x2d4da5db,0x2c07ad96,
0xae5eafa0,0xa934aff4,0x2b05abb7,0xaee928d5,0x2eb51cb6,0x2d962ed0,0x2d962fe6,0x2c87ad72,0x27652f6e,0xaf80ac5d,0xaf46a5db,0xa5152f6e,0xaff4ad4d,0x2ff8244e,0xa17eaee9,0xa875affc,
0xad4d2875,0xafbc217e,0xacd8aff8,0x1fd92ff4,0xaa4eafe6,0x2e99aaaa,0x2fd42993,0xaa4eafc9,0x2fff2c87,0xacb02d96,0xa7652d96,0x2d722eb5,0xab5e2c07,0x2875af30,0xae3faf91,0xaf1aacd8,
0x2d962fbc,0x25db2ffc,0xafdda934,0x2f5a2c07,0xafc9a875,0xaaaaafa0,0x2993ad27,0xafe6a875,0x28d5ad72,0x2d002ed0,0x2d002fe6,0x2ff81cb6,0x2d4d2fd4,0xae5ead96,0xafeda9f1,0xaf9126a1,
0x2e1fa765,0x2ff49cb6,0xa8752ddc,0x2e1facb0,0x1fd92f5a,0xafbc25db,0xacd8afdd,0xad4d2d96,0xaeb5aee9,0x2f5aa934,0x30002b05,0x2c5dae5e,0x2f80230e,0xaed02b5e,0xacb02b5e,0xaaaa2f02,
0xacb0afd4,0x9cb6b000,0x2ddc2f5a,0xa765afd4,0x2ff42c07,0x217e2ffc,0xaff8a934,0x28752fbc,0xadfe28d5,0xa44eaff4,0x2cd8abb7,0xa934afa0,0x1648af46,0x25db2fe6,0x25db2fc9,0x29f12f80,
0xafff9648,0xae7ca6a1,0xafc9a6a1,0x2d722a4e,0x2ff81fd9,0x230e2ee9,0x2faf2814,0x217eaf91,0xafeda30e,0x2d4dafa0,0xaf91a8d5,0xae5e2f02,0x2fdd2515,0xb0002aaa,0x2f6e2993,0x2fdda765,
0xa30e2fff,0xad272fc9,0xad272e7c,0x2fafad72,0x2814afdd,0x2ffcaa4e,0x2dfeadba,0xae5ea5db,0xaa4e2f91,0xac5dac07,0xaeb52cd8,0x96482f30,0x2c32af1a,0xa9932ff4,0x2f46abb7,0x2e7caf1a,
0x2fdd1fd9,0x2dba2814,0x2a4e2ee9,0x25dbaf91,0xaf46a8d5,0x2765afaf,0xa515afaf,0xaf802e1f,0x2e3f2c32,0xafa02ddc,0xa17e2fff,0x2e3f2515,0xacd8adba,0x2dfe26a1,0x2934afd4,0x244eaf6e,
0x2814aff8,0x2dfeafaf,0x2ffca30e,0xae5ea17e,0xac872f46,0xaf5a2515,0xaf5aa765,0xa6a12f80,0x2e7cadba,0x1cb62e99,0x2ddc2c5d,0x2fc9adba,0xafaf2b05,0x2f1aaee9,0xab5eae5e,0xad00a934,
0xaf91a30e,0xacd8a8d5,0x2c07afa0,0xaf302f02,0x2dba2c32,0xac5d2fff,0xae992ddc,0x2dba2515,0xa993aeb5,0x2fc9a9f1,0x2fe6a9f1,0x2aaaafdd,0xa17e2fed,0xa30eadfe,0xafaf9fd9,0xaff82c07,
0xaa4e2fed,0xaeb52f91,0xac5dad4d,0x96482e5e,0x2e7cae3f,0x2ddc217e,0x1cb62fa0,0x2fc9ae3f,0xaff82993,0x2bb7afe6,0x2bb7afc9,0xab5eaaaa,0x2f3025db,0xafbc2a4e,0xaee92dba,0xadfe2fdd,
0x2f1a2515,0x2bb72993,0xaff42aaa,0x2f1aa765,0xab05adba,0x2e5eafd4,0x2ee926a1,0x2934af6e,0xa5db2fed,0xadba9fd9,0xaa4eadfe,0xafdd2c07,0x2ddcaf02,0xacb02ff8,0xa7652ff8,0x9cb62e3f,
0x2c32afdd,0x2f46af6e,0xa9933000,0x2e7cafdd,0xafaf2cd8,0xab5ea934,0x2f1aadfe,0xad00a44e,0x2f30217e,0xaee92faf,0xafbc230e,0xadfe2ff8,0xa9f1addc,0x2c5d2765,0x2c5d2cb0,0x2d961cb6,
0xa993aa4e,0x2765ac87,0xa515ac87,0xaaaa2dba,0xafa02f30,0xabb7244e,0xaff42e5e,0x28d51fd9,0x28142bb7,0xaf912e1f,0x1fd92d27,0x2ee9ad00,0x2fd4aed0,0xaf5a2fff,0x3000addc,0x2fd4afe6,
0xafaf2f46,0xafa02e7c,0xafa02c32,0x2d00a993,0x244e2c5d,0xaf913000,0xab052f5a,0x2fbcaeb5,0x3000adfe,0xac872e5e,0x2e99a814,0x2f6eaffc,0x2515ae1f,0x1cb62875,0x2d72aff4,0x2c32ae1f,
0x26a12b05,0xa9f12cd8,0xad962fed,0x2fd4affc,0x2fffae1f,0x2515230e,0x2c32230e,0x2ddcaf1a,0x2875ae7c,0x2d27aaaa,0x2fa0af80,0x2875ac32,0xaee929f1,0x2f91ae99,0x9fd9ac87,0xa8149648,
0x2fedaf1a,0x2f30ae3f,0x29342875,0x2814ab5e,0x26a1addc,0x3000afc9,0x3000ae7c,0xa5db9cb6,0xaed02a4e,0x2f46afd4,0x2993ae99,0xacb02a4e,0xae3f2ffc,0x2d27ae5e,0xae1f2814,0xaf022dfe,
0x9fd9abb7,0x2c07ad27,0x2fedae1f,0xadfe2d00,0xaf6e2cb0,0x25dba993,0x2c5daf46,0xaf6e2ed0,0xaddc2fdd,0xa5159648,0xac329648,0xafff2fd4,0x28d52814,0xabb72934,0xaff42f30,0xafa02fed,
0xb0002ee9,0xae992dfe,0x2c87af30,0xaf6e2fbc,0xac322f02,0xaf802f1a,0xaaaaa17e,0xae7c2f02,0x2b5e1cb6,0xaff42fc9,0xaff42e7c,0xad272ddc,0x2ffcaeb5,0xafed3000,0xacd82f5a,0xab052c5d,
0xa17e2c32,0xad002d72,0xabb71cb6,0xa17e2515,0x2dfea9f1,0xac072c87,0xafed2e99,0x1fd91648,0x2fd4afbc,0xa9f12b05,0xad962f91,0x26a1a44e,0x2aaaae3f,0xa76528d5,0x251528d5,0x2993a875,
0x2fe6aeb5,0x2ddcadba,0xafff2f6e,0x2ed0aeb5,0x2e3fafbc,0x2e1fadfe,0xad272f30,0x2f02aee9,0x1fd9ab5e,0x2e5eae3f,0x244e2875,0x2f30af1a,0xad962993,0x2e99ae7c,0x2e99ac32,0x2f5aaf46,
0x299329f1,0xa76525db,0x251525db,0x2aaa1648,0x28d52934,0xaf02acd8,0x230e244e,0x2fa02dfe,0x28142875,0xaf91aff8,0x1fd9217e,0x2ee92ff4,0x26a12765,0xaa4eaddc,0x16481cb6,0x26a12cb0,
0x2f022f46,0x2b5e2e7c,0x2b5e2c32,0x230ea993,0x2e5e2eb5,0xab051648,0x29342a4e,0x2ee92c5d,0x2d962dfe,0xafddae5e,0x25db2814,0x2f5a2ffc,0x2cb02d27,0xaddcafaf,0x1cb6230e,0x27652d27,
0x2fd42f91,0x2f6e2fed,0x2dba2e5e,0xa6a1ad4d,0x2fff2ff8,0x25152d00,0x2c322d00,0x2ddc28d5,0x2faf2fe6,0xae1fa993,0x28d52aaa,0x2faf2fc9,0x2ee92f5a,0xaf91afdd,0x1fd925db,0x28142d96,
0x2cd82b5e,0x2f912d00,0x2f302faf,0xac07af1a,0x2eb52ddc,0x2d962fc9,0x2d962e7c,0x2c871cb6,0x2fc92f5a,0xa99326a1,0x2aaa2c87,0x2fe62f5a,0x2ff42ffc,0xaff8ae5e,0x217e2814,0x28752dfe,
0x9fd9a875,0x2c07a17e,0x2fed2ff8,0xadfeaff4,0x29f12515,0x2fdd2f46,0x2eb52f80,0x29f1a765,0x2ddc2c87,0x25152d96,0x2c322d96,0x2fff2eb5,0x2fa02ee9,0xaf02ab05,0x230e2934,0x28d52e5e,
0xad96aee9,0xa5dbadfe,0x2fdd2f30,0xaf5aafbc,0xa765abb7,0x2f462b5e,0x2f802ff8,0x2515abb7,0x28d51cb6,0x2d002fc9,0x2d002e7c,0x2ff82ddc,0x2dfe2c5d,0xacd81648,0x244e2a4e,0x29342eb5,
0xaff8afc9,0xae3fafff,0x2f022d72,0xaff8ae7c,0xadfeaf5a,0x2c07a5db,0x2fed2fdd,0x9fd9ad96,0xa6a1ac07,0x2f6e2f91,0x2dba2f30,0x2fd42cd8,0x2aaa230e,0xa7652b5e,0x25152b5e,0x29932f02,
0xae7cac5d,0xafffad96,0x2d7229f1,0xafc9ac5d,0xaff4afbc,0xa17eadfe,0x2ff82f30,0xa875aee9,0xad4daf1a,0x2fed2d00,0x2e5e2faf,0x2f912b5e,0x1648a993,0x25db2e7c,0x25db2c32,0x29f12f46,
0xaddc9648,0xafe6a6a1,0xaed0a6a1,0x2fff2a4e,0xad27affc,0x2d00ac07,0xabb7afbc,0xae1f2934,0x2e5e230e,0x1fd92fa0,0x2f3028d5,0x244eaf02,0x2c872fe6,0xadbaaf46,0x2a4e2f80,0x2c872fc9,
0xa30e2d72,0xad272c32,0xad272515,0x2faf1cb6,0xafbcae99,0x1fd9af6e,0xad4db000,0xacd82c87,0x2a4eab05,0x2c5d2fbc,0x2eb5244e,0x1648af91,0x2ed02fa0,0xaf80ad00,0x2aaa2faf,0x2cb02fa0,
0x2c872ffc,0x16482fbc,0xa9f12c07,0x2e99a934,0xaf80a8d5,0xac32afaf,0xae7cafaf,0xaaaa2e1f,0xa30eaed0,0x2f1a2d72,0x2e1f9cb6,0xa30eafe6,0x2fed2dba,0xaffca6a1,0x2b052fd4,0x2cd82f6e,
0x2fbc2e1f,0x2d4d2f02,0x9fd92e3f,0x2cd8ad27,0xac872993,0xaf5aacb0,0xaf5aaed0,0xa6a12f46,0xacb0b000,0x2fff25db,0x2d72a6a1,0xa765b000,0x2faf2934,0xaf1a2814,0x2b5e2fed,0x2d002f30,
0x2f30230e,0x2fed28d5,0x28142fa0,0x2934af02,0x16482ed0,0xafd41cb6,0xafddad72,0x16482fe6,0xaf46aeb5,0x2ed0a9f1,0x2cb0a9f1,0xa993afdd,0x2e1fa44e,0xad002d4d,0x2bb72ffc,0x2d272ee9,
0x2a4eacd8,0x2eb5ab05,0x2c5d2ffc,0x1648afed,0x2cb02ff4,0xad722d27,0xafffab5e,0x27652ff4,0xaff8aaaa,0x2bb7ae7c,0x2bb7ac32,0xab5eaf80,0x2b05ac87,0xa8142f6e,0x2c073000,0x2d4d2e99,
0xa8d5afe6,0x2875af80,0x2e3f2f46,0xa8d5afc9,0x2f912dba,0xa44e2fd4,0xafbca6a1,0x2b052f6e,0xae99244e,0x9648affc,0x29f1ad4d,0xac87aee9,0x1cb6af02,0x25152ff8,0x2c322ff8,0x2d722e3f,
0xaed0ae99,0xaaaaaf5a,0x2f802d96,0xacb0ae99,0x2faf244e,0x2b5e2f30,0xaf1a1fd9,0x2d002e5e,0xab052d27,0xac07af02,0x2814ae3f,0xad4dae1f,0xa9f1afff,0x2c5d2ed0,0x2c5d2fe6,0x2d962ddc,
0xaf46aa4e,0xac32ac87,0xae7cac87,0x29932dba,0x2f1a2b05,0xa8752fed,0x2e3f2cd8,0x2b5eaffc,0xaee9abb7,0x2f30ae1f,0xadfead27,0xafbc2d00,0x2eb52c32,0xaf6e1cb6,0x2dba2d72,0x2eb52515,
0xafaf2993,0xafa02515,0xafa0a765,0x2d002aaa,0x2feda6a1,0x29342d96,0x2f3029f1,0x2814afd4,0xb0001fd9,0x2c87afed,0xae99ac07,0xaf6e2dfe,0x2fe6217e,0xafff2bb7,0x2ddc2d00,0x2ed0217e,
0xac5d2f30,0xaf5a2e5e,0xb000244e,0x2eb51fd9,0x2ddcae1f,0x2e7c230e,0x2fc9230e,0x1cb6af1a,0xaf022cb0,0x217eaf46,0xaf1aa993,0xaf022ed0,0x2fbca9f1,0xaf302e99,0x2dfe2c87,0x2ee91648,
0x244e2fa0,0xab052ff4,0xaf912bb7,0x2fbca8d5,0x26a1afff,0x3000ac32,0x3000a515,0xa5dbaddc,0xac322f6e,0xaaaaac5d,0xaf80a5db,0xae7c2f6e,0x2e3fadfe,0xad272fed,0x2e1f2c07,0x2f029fd9,
0x2dfe2bb7,0x28142d27,0xae5e2e1f,0x2ffcad00,0xaa4eae7c,0x2e99af80,0x2fd4aaaa,0xaa4eac32,0x9cb62fdd,0xae7c9648,0xafc99648,0xaddc2fd4,0x2b5eafbc,0xa8752f91,0x2e3f2b05,0x2f1aa44e,
0x3000a814,0x2e999fd9,0xac872f91,0x2f6eaee9,0xaed0a875,0x2993afa0,0x2f46ad27,0xacb0a875,0x2b5e2ddc,0xaff42c32,0xaff42515,0xad272fff,0x1fd9afd4,0x244e2d96,0x2e5e29f1,0x2f30a6a1,
0x2e1faed0,0x2ff4addc,0xa8752fff,0x2e1fafe6,0xaffc29f1,0xa814ac87,0x2e5eae99,0xadfe9648,0x2eb52814,0xaf5a2f30,0xb0002934,0xac5d2fed,0xa993ae3f,0x2c3228d5,0x2e7c28d5,0x2f46a875,
0x2515afd4,0x2d72b000,0x1cb62f5a,0x2c32afd4,0xae3f2ee9,0xae1f1fd9,0x2d27af91,0xaf022814,0x2ffca8d5,0xacd82ff4,0xafed2bb7,0xab052fa0,0xad96aaaa,0x2e99a515,0x2e992765,0x2f5aa993,
0x1cb6adba,0x2cb0aeb5,0x2765aeb5,0xaddc2f6e,0xaff82d4d,0xa30ea814,0xafaf2c07,0xa17e2b05,0xa44e2e3f,0xadfe2b5e,0xa9342f1a,0x2cd8a875,0x2fddacb0,0xb0002f80,0x2f6eaaaa,0x2fddaed0,
0xad009cb6,0xa17ea765,0xa17eacb0,0xabb72ddc,0xaee92fdd,0xad4d2a4e,0xaffc2dba,0x244e25db,0x29f12934,0xafd42ee9,0xa6a12e5e,0x2d96ab05,0x2fc9af1a,0xaf462ff4,0x2f80abb7,0x2fe6af1a,
0xafdd2d4d,0xadba2c07,0xaa4ea814,0xa5db2b05,0xaaaa2f1a,0xafc92f02,0xafe62f02,0x2993a17e,0x2e3fa765,0xafa02fff,0xa17e2d72,0x2e3facb0,0x2e5eb000,0xad4d2eb5,0x2f91ac5d,0x2fedaf5a,
0xaee92ff8,0xaffc2faf,0xad4d230e,0x244e217e,0x25db2aaa,0xaf6e2fe6,0xaf6e2fc9,0x2c5da993,0x2fe6adba,0xad722e99,0x1cb62c5d,0x2ed0adba,0x2bb7af30,0xa8d52c07,0x2fa0acd8,0x2ff4af91,
0xa9342e3f,0xae5e2f1a,0xaee92b5e,0x2b05a875,0x2dbaa765,0xac5d2d72,0xae992fff,0x2dbaacb0,0x2f80afd4,0xa7652a4e,0x25152a4e,0x2f46ae99,0x217eacd8,0x230e1fd9,0x2fafad4d,0x2ff8afbc,
0x29f1244e,0xa6a12934,0xafd42dfe,0x2d96acd8,0x2fe6ae3f,0x1cb6217e,0xad722fa0,0x2ed0ae3f,0x2d27af80,0x2875a515,0x28752765,0x2fa0af46,0xa934a5db,0x2c07aa4e,0x2fbcadba,0x2ffcafdd,
0x2f1aacb0,0x2bb7aaaa,0xaff42f80,0x2f1aaed0,0x2f30b000,0x2cd8ac5d,0xac072eb5,0x2f91af5a,0x25dbacd8,0x2dbaad4d,0x2a4e1fd9,0x2fddafbc,0xad722875,0x2e7cae1f,0x2fc9ae1f,0x2fffaff4,
0x2fc9afdd,0x2f80af6e,0xaf463000,0x2fe6afdd,0x2bb7ae5e,0x2fa0af91,0xa8d52d4d,0x2ff4afed,0xa934a17e,0x2fbcafaf,0x2c07a30e,0x2ffcaff8,0xaf5a2d72,0x2fd4afc9,0x2fd4ae7c,0x3000afff,
0x9d4d9e16,0xada6ae7d,0x9b769c84,0xabf0accf,0x985299e4,0xa897aa43,0x90b6957f,0xa102a5d8,0x13db0a48,0x242c1aad,0x191b1712,0x296d2783,0x1c201aad,0x2c632b1a,0x1db21ce9,0x2e112d3a,
0xa3f4a491,0xae51af42,0xa199a2c6,0xac70ad60,0x9e7ba06b,0xa922ab00,0x97129c20,0xa199a688,0x19e410b6,0x24aa1b76,0x1fa81d4d,0x2a112833,0x222f2102,0x2ce82bf0,0x2445235d,0x2ec92dd8,
0xa6a1a79c,0xaefcb004,0xa4aaa5a5,0xace8adf2,0xa166a35d,0xa9acabbe,0x99e49edf,0xa22fa738,0x1ce913db,0x25281c20,0x2262206b,0x2ab528a4,0x2528242c,0x2d6d2c63,0x271f2623,0x2f822e77,
0xa8a4a954,0xafa8b067,0xa688a7e8,0xad60ae84,0xa38fa528,0xaa37ac3d,0x9c20a0d0,0xa2c6a7e8,0x1edf157f,0x25a51c84,0x2478222f,0x2b592915,0x273825d8,0x2df22ccf,0x28fc284c,0x301d2f16,
0xa9f8aadb,0xb02ab0ca,0xa833a915,0xadd8af16,0xa4dca6a1,0xaac1ac9c,0x9d4da22f,0xa35da84c,0x206b1712,0x26231ce9,0x25bf23f4,0x2bfd2987,0x28a42783,0x2e772d3a,0x2a692987,0x307a2fb5,
0xab4cac31,0xb081b12e,0xa922aa37,0xae51afa8,0xa5f1a80d,0xab4cacfb,0x9e7ba38f,0xa3f4a8a4,0x21661852,0x26a11d4d,0x270524dc,0x2c5029f8,0x29ac2897,0x2efc2da6,0x2bd72ac1,0x30d7302a,
0xac50acf5,0xb0d7b192,0xaa11ab59,0xaec9b01d,0xa705a8ca,0xabd7ad5a,0x9fa8a478,0xa445a8fc,0x2262191b,0x271f1db2,0x282625bf,0x2ca22a69,0x2ab5296d,0x2f822e11,0x2ca22bfd,0x3135307a,
0xacfbadb9,0xb12eb1f7,0xab00ac3d,0xaf42b067,0xa80da987,0xac31adb9,0xa06ba528,0xa491a954,0x235d19e4,0x279c1e16,0x28ca26a1,0x2cf52adb,0x2bbe2a43,0x30042e7d,0x2d5a2c9c,0x319230ca,
0xb185b25c,0xb426b4cc,0xafbbb0b1,0xb1c6b306,0xac76ae18,0xaea3b08a,0xa4dca9ac,0xa738ac37,0x280d1e7b,0x2a0520d0,0x2d472b4c,0x2fdb2d6d,0x30472ee9,0x32663128,0x31f0311b,0x347933a8,
0xb1ddb2c1,0xb453b501,0xb01ab0fb,0xb204b352,0xacbcae77,0xaee9b0ba,0xa528aa05,0xa783ac63,0x284c1edf,0x2a432102,0x2d992bbe,0x30172da6,0x308a2f55,0x32aa315f,0x324f316b,0x34aa33fc,
0xb235b327,0xb481b537,0xb057b145,0xb242b39e,0xad01aed6,0xaf2fb0eb,0xa573aa5d,0xa7cfac90,0x288b1f44,0x2a822134,0x2deb2c18,0x30412ddf,0x30ce2fc2,0x32ef3196,0x32ae31bc,0x34db3428,
0xb28db38e,0xb4afb56d,0xb094b18f,0xb280b3eb,0xad47af36,0xaf75b11b,0xa5bfaab5,0xa80dacbc,0x28ca1fa8,0x2ac12166,0x2e3e2c50,0x306a2e18,0x31113017,0x333531cd,0x330d320e,0x350d3452,
0xb2e5b3f5,0xb4ddb5a3,0xb0d1b1da,0xb2beb41c,0xad8caf95,0xafbbb14b,0xa60aab0d,0xa833ace8,0x29092006,0x2b002199,0x2e902c89,0x30942e51,0x3155304d,0x337a3204,0x336d325f,0x3540347c,
0xb33eb42e,0xb50cb5da,0xb10eb224,0xb2fcb443,0xadd2aff5,0xb001b17c,0xa655ab65,0xa859ad14,0x29482039,0x2b4021cb,0x2ee32cc2,0x30be2e8a,0x31993084,0x33c0323b,0x33cd32b1,0x357234a6,
0xb398b463,0xb53ab612,0xb14bb26f,0xb33bb469,0xae18b02a,0xb024b1ac,0xa6a1abbe,0xa87ead40,0x2987206b,0x2b7f21fd,0x2f362cfb,0x30e72ec3,0x31dd30ba,0x34033273,0x34173303,0x35a534d1,
0xb3f2b497,0xb569b64a,0xb189b2bb,0xb37ab490,0xae5eb05a,0xb047b1dd,0xa6ecac0b,0xa8a4ad6d,0x29c6209d,0x2bbe222f,0x2f882d34,0x31112efc,0x322130f1,0x342632aa,0x34483356,0x35d934fc,
0xb599b682,0xb722b82e,0xb3b9b4b7,0xb4ddb5f9,0xb06ab20e,0xb185b398,0xa8caad99,0xa9f8aefc,0x2bfd2262,0x2cfb23f4,0x313b2f36,0x328d3081,0x344932e2,0x35693453,0x360d3527,0x37bd368b,
0xb5c9b6bb,0xb755b84d,0xb3f8b4df,0xb4feb622,0xb08db23e,0xb1a9b3ca,0xa8f0adc5,0xaa1eaf29,0x2c1e2294,0x2d1b2413,0x31652f6f,0x32b7309d,0x346d331a,0x358e3470,0x36413553,0x37f536ba,
0xb5f9b6f5,0xb789b86d,0xb41cb506,0xb51fb64c,0xb0b1b26f,0xb1cdb3fc,0xa915adf2,0xaa43af55,0x2c3d22c6,0x2d3a242c,0x318f2fa8,0x32e230ba,0x34903352,0x35b3348d,0x3676357e,0x381736e8,
0xb629b72f,0xb7bdb88d,0xb43cb52e,0xb540b676,0xb0d4b2a1,0xb1f0b417,0xa93bae1e,0xaa69af82,0x2c5d22f9,0x2d5a2445,0x31b92fe2,0x330d30d7,0x34b4338b,0x35d934aa,0x36ab35ab,0x38343717,
0xb65ab76a,0xb7f1b8ad,0xb45cb556,0xb561b6a0,0xb0f7b2d2,0xb214b430,0xa961ae4b,0xaa8fafaf,0x2c7d232b,0x2d79245f,0x31e3300e,0x333830f4,0x34d833c3,0x35fe34c7,0x36e035d7,0x38513746,
0xb68bb7a5,0xb813b8ce,0xb47cb57e,0xb582b6ca,0xb11bb303,0xb238b449,0xa987ae77,0xaab5afdb,0x2c9c235d,0x2d992478,0x320e302a,0x33633111,0x34fc33fc,0x362434e4,0x37173604,0x386f3775,
0xb6bdb7e2,0xb82eb8f0,0xb49cb5a7,0xb5a3b6f5,0xb13eb335,0xb25cb463,0xa9acaea3,0xaadbb004,0x2cbc238f,0x2db92491,0x32383047,0x338e312e,0x3520341a,0x364a3501,0x374d3631,0x388d37a5,
0xb6efb80f,0xb849b911,0xb4bdb5d0,0xb5c5b720,0xb162b366,0xb280b47c,0xa9d2aed0,0xab00b01a,0x2cdb23c2,0x2dd824aa,0x32623064,0x33b9314b,0x35453437,0x3670351f,0x3785365e,0x38ab37d6,
0xb865b934,0xb94dba5c,0xb5e7b74c,0xb6fcb85a,0xb2a4b495,0xb3c6b564,0xab26b031,0xac2bb0e4,0x2df824c3,0x2ef6258c,0x33e43168,0x34a13252,0x3697353c,0x37d4362d,0x38ca3803,0x39d038d0,
0xb880b957,0xb96bba84,0xb609b777,0xb720b872,0xb2c8b4af,0xb3ebb57e,0xab4cb047,0xac3db0fb,0x2e1824dc,0x2f1625a5,0x34083185,0x34b7326f,0x36bd355a,0x37fd364c,0x38e9381c,0x39f338eb,
0xb89cb97a,0xb98abaad,0xb62bb7a4,0xb744b88a,0xb2ecb4c9,0xb408b599,0xab72b05d,0xac50b111,0x2e3724f5,0x2f3625bf,0x341e31a2,0x34ce328d,0x36e43577,0x3813366b,0x39093835,0x3a173906,
0xb8b9b99e,0xb9aabad7,0xb64db7d0,0xb768b8a2,0xb310b4e2,0xb41ab5b3,0xab98b074,0xac63b128,0x2e57250f,0x2f5525d8,0x343331c0,0x34e432aa,0x370b3595,0x3828368a,0x3929384e,0x3a3b3922,
0xb8d6b9c3,0xb9cabb02,0xb670b7fd,0xb78cb8ba,0xb335b4fc,0xb42db5ce,0xabbeb08a,0xac76b13e,0x2e772528,0x2f7525f1,0x344931dd,0x34fa32c8,0x373335b3,0x383d36a9,0x39493868,0x3a60393e,
0xb8f3b9e8,0xb9ebbb2d,0xb693b815,0xb7b1b8d2,0xb359b516,0xb43fb5e9,0xabe3b0a1,0xac89b155,0x2e972541,0x2f95260a,0x345f31fa,0x351132e5,0x375b35d2,0x385236c8,0x396a3881,0x3a86395a,
0xb910ba0e,0xba0cbb59,0xb6b6b82c,0xb7d6b8eb,0xb37db530,0xb452b604,0xac05b0b7,0xac9cb16b,0x2eb6255a,0x2fb52623,0x34753217,0x35273303,0x378335f0,0x386836e8,0x398c389b,0x3aac3977,
0xb92eba35,0xba2dbb87,0xb6d9b843,0xb7fbb904,0xb3a2b54a,0xb464b61e,0xac18b0ce,0xacafb182,0x2ed62573,0x2fd5263c,0x348b3235,0x353e3321,0x37ab360e,0x387d3708,0x39ae38b6,0x3ad33994,
0x9ce99db2,0xad3aae11,0x9aad9c20,0xab1aac63,0x9712991b,0xa783a96d,0x8a4893db,0x9aada42c,0x157f10b6,0x25d82102,0x19e41852,0x2a432897,0x1c841b76,0x2ccf2bf0,0x1e161d4d,0x2e7d2da6,
0xa35da445,0xadd8aec9,0xa102a22f,0xabf0ace8,0x9d4d9fa8,0xa833aa11,0x90b699e4,0x9b76a4aa,0x1c201712,0x26882199,0x206b1e7b,0x2b002922,0x22c62199,0x2d602c70,0x249123f4,0x2f422e51,
0xa623a71f,0xae77af82,0xa42ca528,0xac63ad6d,0xa06ba262,0xa8a4aab5,0x93db9ce9,0x9c20a528,0x1edf19e4,0x2738222f,0x235d2166,0x2bbe29ac,0x25a524aa,0x2df22ce8,0x279c26a1,0x30042efc,
0xa84ca8fc,0xaf16b01d,0xa5d8a738,0xaccfadf2,0xa22fa478,0xa915ab59,0x957f9edf,0x9c84a5a5,0x20d01c20,0x27e822c6,0x2528238f,0x2c3d2a37,0x27e82688,0x2e842d60,0x295428a4,0x30672fa8,
0xa987aa69,0xafb5b07a,0xa783a8a4,0xad3aae77,0xa3f4a5bf,0xa987abfd,0x9712a06b,0x9ce9a623,0x222f1d4d,0x284c235d,0x26a124dc,0x2c9c2ac1,0x29152833,0x2f162dd8,0x2adb29f8,0x30ca302a,
0xaac1abd7,0xb02ab0d7,0xa897a9ac,0xada6aefc,0xa4dca705,0xa9f8ac50,0x9852a166,0x9d4da6a1,0x238f1e7b,0x28a423f4,0x280d25f1,0x2cfb2b4c,0x2a372922,0x2fa82e51,0x2c312b4c,0x312e3081,
0xabfdaca2,0xb07ab135,0xa96daab5,0xae11af82,0xa5bfa826,0xaa69aca2,0x991ba262,0x9db2a71f,0x24781fa8,0x28fc2445,0x28ca2705,0x2d5a2bd7,0x2b592a11,0x301d2ec9,0x2cf52c50,0x319230d7,
0xac9cad5a,0xb0cab192,0xaa43abbe,0xae7db004,0xa6a1a8ca,0xaadbacf5,0x99e4a35d,0x9e16a79c,0x2528206b,0x29542491,0x2987280d,0x2db92c31,0x2c3d2b00,0x30672f42,0x2db92cfb,0x31f7312e,
0xb11bb1f0,0xb3a8b479,0xaee9b047,0xb128b266,0xab4cad47,0xad6dafdb,0x9e7ba80d,0xa0d0aa05,0x29ac24dc,0x2c372738,0x2e182c76,0x308a2ea3,0x30b12fbb,0x330631c6,0x325c3185,0x34cc3426,
0xb16bb24f,0xb3fcb4aa,0xaf55b08a,0xb15fb2aa,0xabbead99,0xada6b017,0x9edfa84c,0xa102aa43,0x2a052528,0x2c632783,0x2e772cbc,0x30ba2ee9,0x30fb301a,0x33523204,0x32c131dd,0x35013453,
0xb1bcb2ae,0xb428b4db,0xafc2b0ce,0xb196b2ef,0xac18adeb,0xaddfb041,0x9f44a88b,0xa134aa82,0x2a5d2573,0x2c9027cf,0x2ed62d01,0x30eb2f2f,0x31453057,0x339e3242,0x33273235,0x35373481,
0xb20eb30d,0xb452b50d,0xb017b111,0xb1cdb335,0xac50ae3e,0xae18b06a,0x9fa8a8ca,0xa166aac1,0x2ab525bf,0x2cbc280d,0x2f362d47,0x311b2f75,0x318f3094,0x33eb3280,0x338e328d,0x356d34af,
0xb25fb36d,0xb47cb540,0xb04db155,0xb204b37a,0xac89ae90,0xae51b094,0xa006a909,0xa199ab00,0x2b0d260a,0x2ce82833,0x2f952d8c,0x314b2fbb,0x31da30d1,0x341c32be,0x33f532e5,0x35a334dd,
0xb2b1b3cd,0xb4a6b572,0xb084b199,0xb23bb3c0,0xacc2aee3,0xae8ab0be,0xa039a948,0xa1cbab40,0x2b652655,0x2d142859,0x2ff52dd2,0x317c3001,0x3224310e,0x344332fc,0x342e333e,0x35da350c,
0xb303b417,0xb4d1b5a5,0xb0bab1dd,0xb273b403,0xacfbaf36,0xaec3b0e7,0xa06ba987,0xa1fdab7f,0x2bbe26a1,0x2d40287e,0x302a2e18,0x31ac3024,0x326f314b,0x3469333b,0x34633398,0x3612353a,
0xb356b448,0xb4fcb5d9,0xb0f1b221,0xb2aab426,0xad34af88,0xaefcb111,0xa09da9c6,0xa22fabbe,0x2c0b26ec,0x2d6d28a4,0x305a2e5e,0x31dd3047,0x32bb3189,0x3490337a,0x349733f2,0x364a3569,
0xb527b60d,0xb68bb7bd,0xb2e2b449,0xb453b569,0xaf36b13b,0xb081b28d,0xa262abfd,0xa3f4acfb,0x2d9928ca,0x2efc29f8,0x320e306a,0x33983185,0x34b733b9,0x35f934dd,0x36823599,0x382e3722,
0xb553b641,0xb6bab7f5,0xb31ab46d,0xb470b58e,0xaf6fb165,0xb09db2b7,0xa294ac1e,0xa413ad1b,0x2dc528f0,0x2f292a1e,0x323e308d,0x33ca31a9,0x34df33f8,0x362234fe,0x36bb35c9,0x384d3755,
0xb57eb676,0xb6e8b817,0xb352b490,0xb48db5b3,0xafa8b18f,0xb0bab2e2,0xa2c6ac3d,0xa42cad3a,0x2df22915,0x2f552a43,0x326f30b1,0x33fc31cd,0x3506341c,0x364c351f,0x36f535f9,0x386d3789,
0xb5abb6ab,0xb717b834,0xb38bb4b4,0xb4aab5d9,0xafe2b1b9,0xb0d7b30d,0xa2f9ac5d,0xa445ad5a,0x2e1e293b,0x2f822a69,0x32a130d4,0x341731f0,0x352e343c,0x36763540,0x372f3629,0x388d37bd,
0xb5d7b6e0,0xb746b851,0xb3c3b4d8,0xb4c7b5fe,0xb00eb1e3,0xb0f4b338,0xa32bac7d,0xa45fad79,0x2e4b2961,0x2faf2a8f,0x32d230f7,0x34303214,0x3556345c,0x36a03561,0x376a365a,0x38ad37f1,
0xb604b717,0xb775b86f,0xb3fcb4fc,0xb4e4b624,0xb02ab20e,0xb111b363,0xa35dac9c,0xa478ad99,0x2e772987,0x2fdb2ab5,0x3303311b,0x34493238,0x357e347c,0x36ca3582,0x37a5368b,0x38ce3813,
0xb631b74d,0xb7a5b88d,0xb41ab520,0xb501b64a,0xb047b238,0xb12eb38e,0xa38facbc,0xa491adb9,0x2ea329ac,0x30042adb,0x3335313e,0x3463325c,0x35a7349c,0x36f535a3,0x37e236bd,0x38f0382e,
0xb65eb785,0xb7d6b8ab,0xb437b545,0xb51fb670,0xb064b262,0xb14bb3b9,0xa3c2acdb,0xa4aaadd8,0x2ed029d2,0x301a2b00,0x33663162,0x347c3280,0x35d034bd,0x372035c5,0x380f36ef,0x39113849,
0xb803b8ca,0xb8d0b9d0,0xb53cb697,0xb62db7d4,0xb168b3e4,0xb252b4a1,0xa4c3adf8,0xa58caef6,0x30312b26,0x30e42c2b,0x349532a4,0x356433c6,0x374c35e7,0x385a36fc,0x39343865,0x3a5c394d,
0xb81cb8e9,0xb8ebb9f3,0xb55ab6bd,0xb64cb7fd,0xb185b408,0xb26fb4b7,0xa4dcae18,0xa5a5af16,0x30472b4c,0x30fb2c3d,0x34af32c8,0x357e33eb,0x37773609,0x38723720,0x39573880,0x3a84396b,
0xb835b909,0xb906ba17,0xb577b6e4,0xb66bb813,0xb1a2b41e,0xb28db4ce,0xa4f5ae37,0xa5bfaf36,0x305d2b72,0x31112c50,0x34c932ec,0x35993408,0x37a4362b,0x388a3744,0x397a389c,0x3aad398a,
0xb84eb929,0xb922ba3b,0xb595b70b,0xb68ab828,0xb1c0b433,0xb2aab4e4,0xa50fae57,0xa5d8af55,0x30742b98,0x31282c63,0x34e23310,0x35b3341a,0x37d0364d,0x38a23768,0x399e38b9,0x3ad739aa,
0xb868b949,0xb93eba60,0xb5b3b733,0xb6a9b83d,0xb1ddb449,0xb2c8b4fa,0xa528ae77,0xa5f1af75,0x308a2bbe,0x313e2c76,0x34fc3335,0x35ce342d,0x37fd3670,0x38ba378c,0x39c338d6,0x3b0239ca,
0xb881b96a,0xb95aba86,0xb5d2b75b,0xb6c8b852,0xb1fab45f,0xb2e5b511,0xa541ae97,0xa60aaf95,0x30a12be3,0x31552c89,0x35163359,0x35e9343f,0x38153693,0x38d237b1,0x39e838f3,0x3b2d39eb,
0xb89bb98c,0xb977baac,0xb5f0b783,0xb6e8b868,0xb217b475,0xb303b527,0xa55aaeb6,0xa623afb5,0x30b72c05,0x316b2c9c,0x3530337d,0x36043452,0x382c36b6,0x38eb37d6,0x3a0e3910,0x3b593a0c,
0xb8b6b9ae,0xb994bad3,0xb60eb7ab,0xb708b87d,0xb235b48b,0xb321b53e,0xa573aed6,0xa63cafd5,0x30ce2c18,0x31822caf,0x354a33a2,0x361e3464,0x384336d9,0x390437fb,0x3a35392e,0x3b873a2d,
0x214d2216,0x319b326c,0x1f762084,0x2fe830c8,0x1c521de4,0x2c962e40,0x14b6197f,0x250229d7,0x97db8e48,0xa82c9ead,0x9d1b9b12,0xad6bab82,0xa0209ead,0xb05eaf14,0xa1b2a0e9,0xb204b131,
0x27f32890,0x3241332b,0x259826c6,0x306a3156,0x227b246b,0x2d202efb,0x1b122020,0x25982a87,0x9de494b6,0xa8aa9f76,0xa3a8a14d,0xae0eac32,0xa62fa502,0xb0e1afe8,0xa845a75d,0xb2b6b1cc,
0x2aa02b9b,0x32e733e8,0x28aa29a5,0x30e131e5,0x2566275d,0x2daa2fb6,0x1de422df,0x262f2b36,0xa0e997db,0xa927a020,0xa661a46b,0xaeb0aca2,0xa927a82c,0xb163b05e,0xab1daa22,0xb368b266,
0x2ca22d52,0x338d3452,0x2a872be6,0x31563273,0x278f2927,0x2e333039,0x202024cf,0x26c62be6,0xa2df997f,0xa9a5a084,0xa877a62f,0xaf53ad13,0xab36a9d7,0xb1e5b0c8,0xacfaac4b,0xb40cb300,
0x2df52ed6,0x341834b0,0x2c322d13,0x31cc3300,0x28dc2aa0,0x2ebd3096,0x214d262f,0x275d2c4b,0xa46b9b12,0xaa22a0e9,0xa9bea7f3,0xaff5ad84,0xaca2ab82,0xb266b131,0xae65ad84,0xb464b399,
0x2f46302c,0x346a350c,0x2d202e33,0x3241338d,0x29f02c0c,0x2f4630f3,0x227b278f,0x27f32ca2,0xa5669c52,0xaaa0a14d,0xab04a8dc,0xb04badf5,0xadaaac96,0xb2e7b19b,0xafcfaebd,0xb4bcb418,
0x304b30ed,0x34bc3568,0x2e0e2f53,0x32b6340c,0x2b042cc8,0x2fcf3150,0x23a82877,0x28452cfa,0xa6619d1b,0xab1da1b2,0xac25a9be,0xb09cae65,0xaeb0ad6b,0xb368b204,0xb09caff5,0xb512b464,
0x30f331ad,0x350c35c4,0x2efb3039,0x332b3452,0x2c0c2d84,0x302c31ad,0x246b2927,0x28902d52,0xa75d9de4,0xab9ba216,0xacc8aaa0,0xb0edaed6,0xafb6ae40,0xb3e8b26c,0xb150b096,0xb568b4b0,
0x355d361e,0x37c63867,0x339f3497,0x359836b4,0x3071320a,0x32913473,0x28dc2daa,0x2b363032,0xac0ca27b,0xae01a4cf,0xb13eaf46,0xb3bdb163,0xb434b2d5,0xb627b506,0xb5beb4fa,0xb826b73e,
0x35ac3678,0x3808388f,0x340934dd,0x35cf36f5,0x30b53266,0x32d534a0,0x29272e01,0x2b82305e,0xac4ba2df,0xae40a502,0xb18eafb6,0xb406b19b,0xb473b33d,0xb663b539,0xb612b545,0xb84cb784,
0x35fb36d0,0x382c38b7,0x34433521,0x36073736,0x30f932c2,0x331834ce,0x29722e59,0x2bcd308a,0xac89a344,0xae7ea534,0xb1dfb013,0xb42eb1d2,0xb4b3b3a5,0xb6a0b56b,0xb666b58f,0xb872b7c9,
0x36493728,0x385038de,0x347c3565,0x363e3776,0x313e331e,0x335c34fa,0x29be2eb0,0x2c0c30b5,0xacc8a3a8,0xaebda566,0xb22fb04b,0xb455b20a,0xb4f1b406,0xb6dcb59d,0xb6b9b5d8,0xb898b807,
0x3697377e,0x38743904,0x34b635a9,0x367537b6,0x3182337a,0x339f3527,0x2a092f08,0x2c3230e1,0xad07a406,0xaefba598,0xb27fb083,0xb47cb241,0xb530b43a,0xb717b5cf,0xb70cb621,0xb8bdb828,
0x36e437d4,0x3897392a,0x34ee35ed,0x36ab37f5,0x31c633d6,0x33e23554,0x2a542f5f,0x2c57310c,0xad45a439,0xaf3aa5cb,0xb2cfb0bb,0xb4a4b279,0xb56eb46d,0xb752b601,0xb75db669,0xb8e1b84a,
0x37303814,0x38b9394e,0x3527362f,0x36e1381a,0x320a3418,0x34123580,0x2aa02fb6,0x2c7d3137,0xad84a46b,0xaf78a5fd,0xb31eb0f3,0xb4cbb2b0,0xb5acb4a0,0xb78cb632,0xb7adb6b1,0xb905b86b,
0x377c383e,0x38db3972,0x355f3672,0x37173838,0x324e3446,0x343435ac,0x2aeb3007,0x2ca23163,0xadc3a49d,0xafb6a62f,0xb36eb12b,0xb4f1b2e7,0xb5eab4d4,0xb7c6b663,0xb7fdb6f8,0xb928b88b,
0x38fd3996,0x39f33a91,0x374c3857,0x3874393e,0x345535d8,0x355d3730,0x2cc8318e,0x2df532e7,0xaff5a661,0xb0f3a7f3,0xb518b31e,0xb649b46a,0xb800b694,0xb8dbb808,0xb94bb8ab,0xba45b99b,
0x391e39b8,0x3a0f3aad,0x37813875,0x388c3959,0x34763604,0x357d375a,0x2cee31b9,0x2e1a3312,0xb01aa694,0xb112a813,0xb53fb356,0xb66fb485,0xb81cb6c5,0xb8f5b81f,0xb96db8cb,0xba61b9b7,
0x393e39da,0x3a2b3ac7,0x37b63893,0x38a53974,0x3497362f,0x359d3784,0x2d1331e5,0x2e40333d,0xb039a6c6,0xb131a82c,0xb565b38d,0xb694b4a0,0xb838b6f5,0xb90fb836,0xb98eb8ea,0xba7cb9d2,
0x395e39fb,0x3a453ae0,0x37ea38b0,0x38bd398e,0x34b9365b,0x35be37ad,0x2d393210,0x2e653368,0xb058a6f8,0xb150a845,0xb58cb3c3,0xb6b9b4bc,0xb854b725,0xb928b84c,0xb9aeb909,0xba97b9ed,
0x397d3a1b,0x3a5f3af9,0x380f38cd,0x38d539a8,0x34da3686,0x35de37d7,0x2d5e323b,0x2e8b3393,0xb077a72a,0xb16fa85e,0xb5b2b3fa,0xb6deb4d7,0xb870b755,0xb941b863,0xb9ceb927,0xbab0ba07,
0x399b3a3a,0x3a793b10,0x382838ea,0x38ed39c1,0x34fa36b1,0x35fe3800,0x2d843266,0x2eb033bd,0xb096a75d,0xb18ea877,0xb5d8b418,0xb703b4f1,0xb88bb784,0xb95ab879,0xb9edb945,0xbac9ba21,
0x39b93a58,0x3a913b26,0x38423906,0x390439da,0x351b36dc,0x361e3814,0x2daa3291,0x2ed633e8,0xb0b5a78f,0xb1ada890,0xb5feb434,0xb728b50c,0xb8a6b7b3,0xb972b88f,0xba0bb962,0xbae0ba3a,
0x39d73a75,0x3aa93b3c,0x385b3922,0x391b39f2,0x353c3706,0x363e3828,0x2dcf32bc,0x2efb3409,0xb0d4a7c1,0xb1cca8aa,0xb624b44f,0xb74cb527,0xb8c1b7e2,0xb98ab8a5,0xba29b97f,0xbaf7ba52,
0x3ac03b50,0x3b5e3bcb,0x39323a0a,0x39de3ab8,0x365e383c,0x375738d7,0x2f21341f,0x302634c8,0xb1eba8c3,0xb2e1a98c,0xb770b542,0xb846b615,0xb9a2b8bb,0xba51b960,0xbb0dba6a,0xbb9cbb11,
0x3ad73b63,0x3b6e3bd6,0x39493a22,0x39f23acb,0x367d3850,0x377638ea,0x2f463434,0x303934dd,0xb20aa8dc,0xb300a9a5,0xb795b55d,0xb857b62f,0xb9b9b8d0,0xba65b974,0xbb22ba81,0xbba9bb24,
0x3aec3b75,0x3b7d3bdf,0x395f3a39,0x3a063ade,0x369d3864,0x379538fd,0x2f6c3449,0x304b34f1,0xb229a8f5,0xb31ea9be,0xb7b8b577,0xb868b649,0xb9d0b8e5,0xba79b987,0xbb36ba97,0xbbb6bb35,
0x3b013b86,0x3b8c3be7,0x39753a4f,0x3a193af0,0x36bc3878,0x37b3390f,0x2f91345e,0x305e3506,0xb247a90e,0xb33da9d7,0xb7dcb592,0xb879b663,0xb9e7b8fa,0xba8cb99a,0xbb4abaad,0xbbc2bb46,
0x3b153b96,0x3b993bee,0x398a3a65,0x3a2d3b02,0x36dc388b,0x37d13921,0x2fb63473,0x3071351b,0xb266a927,0xb35ca9f0,0xb800b5ac,0xb88ab67d,0xb9fdb90f,0xba9fb9ad,0xbb5cbac3,0xbbccbb56,
0x3b283ba5,0x3ba63bf4,0x39a03a7a,0x3a3f3b13,0x36fb389e,0x37ef3933,0x2fdc3488,0x30833530,0xb285a940,0xb37aaa09,0xb811b5c7,0xb89bb697,0xba12b924,0xbab1b9c0,0xbb6dbad7,0xbbd6bb65,
0x3b3b3bb3,0x3bb23bf9,0x39b53a8f,0x3a523b24,0x371a38b2,0x38073945,0x3001349d,0x30963545,0xb2a4a959,0xb399aa22,0xb823b5e1,0xb8abb6b1,0xba28b938,0xbac3b9d2,0xbb7ebaeb,0xbbdfbb74,
0x3b4d3bc0,0x3bbd3bfc,0x39ca3aa4,0x3a643b34,0x373938c5,0x38153957,0x301334b3,0x30a9355a,0xb2c2a972,0xb3b7aa3b,0xb834b5fb,0xb8bcb6ca,0xba3cb94c,0xbad4b9e4,0xbb8dbaff,0xbbe6bb82,
0x20e921b2,0x31313204,0x1ead2020,0x2f14305e,0x1b121d1b,0x2b822d6b,0xe4817db,0x1ead282c,0x997f94b6,0xa9d7a502,0x9de49c52,0xae40ac96,0xa0849f76,0xb0c8afe8,0xa216a14d,0xb26cb19b,
0x275d2845,0x31cc32b6,0x2502262f,0x2fe830e1,0x214d23a8,0x2c322e0e,0x14b61de4,0x1f7628aa,0xa0209b12,0xaa87a598,0xa46ba27b,0xaefbad20,0xa6c6a598,0xb156b06a,0xa890a7f3,0xb32bb241,
0x2a222b1d,0x32663368,0x282c2927,0x305e3163,0x246b2661,0x2ca22eb0,0x17db20e9,0x20202927,0xa2df9de4,0xab36a62f,0xa75da566,0xafb6adaa,0xa9a5a8aa,0xb1e5b0e1,0xab9baaa0,0xb3e8b2e7,
0x2c4b2cfa,0x3300340c,0x29d72b36,0x30c831e5,0x262f2877,0x2d132f53,0x197f22df,0x208429a5,0xa4cfa020,0xabe6a6c6,0xa927a78f,0xb039ae33,0xabe6aa87,0xb273b156,0xad52aca2,0xb452b38d,
0x2d842e65,0x33993464,0x2b822ca2,0x31313266,0x27f329be,0x2d842ff5,0x1b12246b,0x20e92a22,0xa62fa14d,0xac4ba75d,0xaaa0a8dc,0xb096aebd,0xad13ac32,0xb300b1cc,0xaed6adf5,0xb4b0b418,
0x2ebd2fcf,0x341834bc,0x2c962daa,0x319b32e7,0x28dc2b04,0x2df5304b,0x1c522566,0x214d2aa0,0xa78fa27b,0xaca2a7f3,0xac0ca9f0,0xb0f3af46,0xae33ad20,0xb38db241,0xb02caf46,0xb50cb46a,
0x2ff5309c,0x34643512,0x2d6b2eb0,0x32043368,0x29be2c25,0x2e65309c,0x1d1b2661,0x21b22b1d,0xa877a3a8,0xacfaa845,0xacc8ab04,0xb150afcf,0xaf53ae0e,0xb40cb2b6,0xb0edb04b,0xb568b4bc,
0x30963150,0x34b03568,0x2e402fb6,0x326c33e8,0x2aa02cc8,0x2ed630ed,0x1de4275d,0x22162b9b,0xa927a46b,0xad52a890,0xad84ac0c,0xb1adb02c,0xb039aefb,0xb452b32b,0xb1adb0f3,0xb5c4b50c,
0x34fa35be,0x373e3826,0x32d53434,0x35063627,0x2f46313e,0x316333bd,0x227b2c0c,0x24cf2e01,0xadaaa8dc,0xb032ab36,0xb20ab071,0xb473b291,0xb497b39f,0xb6b4b598,0xb61eb55d,0xb867b7c6,
0x35453612,0x3784384c,0x333d3473,0x35393663,0x2fb6318e,0x319b3406,0x22df2c4b,0x25022e40,0xae01a927,0xb05eab82,0xb266b0b5,0xb4a0b2d5,0xb4ddb409,0xb6f5b5cf,0xb678b5ac,0xb88fb808,
0x358f3666,0x37c93872,0x33a534b3,0x356b36a0,0x301331df,0x31d2342e,0x23442c89,0x25342e7e,0xae59a972,0xb08aabcd,0xb2c2b0f9,0xb4ceb318,0xb521b443,0xb736b607,0xb6d0b5fb,0xb8b7b82c,
0x35d836b9,0x38073898,0x340634f1,0x359d36dc,0x304b322f,0x320a3455,0x23a82cc8,0x25662ebd,0xaeb0a9be,0xb0b5ac0c,0xb31eb13e,0xb4fab35c,0xb565b47c,0xb776b63e,0xb728b649,0xb8deb850,
0x3621370c,0x382838bd,0x343a3530,0x35cf3717,0x3083327f,0x3241347c,0x24062d07,0x25982efb,0xaf08aa09,0xb0e1ac32,0xb37ab182,0xb527b39f,0xb5a9b4b6,0xb7b6b675,0xb77eb697,0xb904b874,
0x3669375d,0x384a38e1,0x346d356e,0x36013752,0x30bb32cf,0x327934a4,0x24392d45,0x25cb2f3a,0xaf5faa54,0xb10cac57,0xb3d6b1c6,0xb554b3e2,0xb5edb4ee,0xb7f5b6ab,0xb7d4b6e4,0xb92ab897,
0x36b137ad,0x386b3905,0x34a035ac,0x3632378c,0x30f3331e,0x32b034cb,0x246b2d84,0x25fd2f78,0xafb6aaa0,0xb137ac7d,0xb418b20a,0xb580b412,0xb62fb527,0xb81ab6e1,0xb814b730,0xb94eb8b9,
0x36f837fd,0x388b3928,0x34d435ea,0x366337c6,0x312b336e,0x32e734f1,0x249d2dc3,0x262f2fb6,0xb007aaeb,0xb163aca2,0xb446b24e,0xb5acb434,0xb672b55f,0xb838b717,0xb83eb77c,0xb972b8db,
0x38ab394b,0x399b3a45,0x36943800,0x380838db,0x331e3518,0x346a3649,0x26612ff5,0x27f330f3,0xb18eacc8,0xb2e7adf5,0xb5d8b455,0xb730b55d,0xb857b74c,0xb93eb874,0xb996b8fd,0xba91b9f3,
0x38cb396d,0x39b73a61,0x36c5381c,0x381f38f5,0x3356353f,0x3485366f,0x2694301a,0x28133112,0xb1b9acee,0xb312ae1a,0xb604b476,0xb75ab57d,0xb875b781,0xb959b88c,0xb9b8b91e,0xbaadba0f,
0x38ea398e,0x39d23a7c,0x36f53838,0x3836390f,0x338d3565,0x34a03694,0x26c63039,0x282c3131,0xb1e5ad13,0xb33dae40,0xb62fb497,0xb784b59d,0xb893b7b6,0xb974b8a5,0xb9dab93e,0xbac7ba2b,
0x390939ae,0x39ed3a97,0x37253854,0x384c3928,0x33c3358c,0x34bc36b9,0x26f83058,0x28453150,0xb210ad39,0xb368ae65,0xb65bb4b9,0xb7adb5be,0xb8b0b7ea,0xb98eb8bd,0xb9fbb95e,0xbae0ba45,
0x392739ce,0x3a073ab0,0x37553870,0x38633941,0x33fa35b2,0x34d736de,0x272a3077,0x285e316f,0xb23bad5e,0xb393ae8b,0xb686b4da,0xb7d7b5de,0xb8cdb80f,0xb9a8b8d5,0xba1bb97d,0xbaf9ba5f,
0x394539ed,0x3a213ac9,0x3784388b,0x3879395a,0x341835d8,0x34f13703,0x275d3096,0x2877318e,0xb266ad84,0xb3bdaeb0,0xb6b1b4fa,0xb800b5fe,0xb8eab828,0xb9c1b8ed,0xba3ab99b,0xbb10ba79,
0x39623a0b,0x3a3a3ae0,0x37b338a6,0x388f3972,0x343435fe,0x350c3728,0x278f30b5,0x289031ad,0xb291adaa,0xb3e8aed6,0xb6dcb51b,0xb814b61e,0xb906b842,0xb9dab904,0xba58b9b9,0xbb26ba91,
0x397f3a29,0x3a523af7,0x37e238c1,0x38a5398a,0x344f3624,0x3527374c,0x27c130d4,0x28aa31cc,0xb2bcadcf,0xb409aefb,0xb706b53c,0xb828b63e,0xb922b85b,0xb9f2b91b,0xba75b9d7,0xbb3cbaa9,
0x3a6a3b0d,0x3b113b9c,0x38bb39a2,0x39603a51,0x35423770,0x36153846,0x28c331eb,0x298c32e1,0xb41faf21,0xb4c8b026,0xb83cb65e,0xb8d7b757,0xba0ab932,0xbab8b9de,0xbb50bac0,0xbbcbbb5e,
0x3a813b22,0x3b243ba9,0x38d039b9,0x39743a65,0x355d3795,0x362f3857,0x28dc320a,0x29a53300,0xb434af46,0xb4ddb039,0xb850b67d,0xb8eab776,0xba22b949,0xbacbb9f2,0xbb63bad7,0xbbd6bb6e,
0x3a973b36,0x3b353bb6,0x38e539d0,0x39873a79,0x357737b8,0x36493868,0x28f53229,0x29be331e,0xb449af6c,0xb4f1b04b,0xb864b69d,0xb8fdb795,0xba39b95f,0xbadeba06,0xbb75baec,0xbbdfbb7d,
0x3aad3b4a,0x3b463bc2,0x38fa39e7,0x399a3a8c,0x359237dc,0x36633879,0x290e3247,0x29d7333d,0xb45eaf91,0xb506b05e,0xb878b6bc,0xb90fb7b3,0xba4fb975,0xbaf0ba19,0xbb86bb01,0xbbe7bb8c,
0x3ac33b5c,0x3b563bcc,0x390f39fd,0x39ad3a9f,0x35ac3800,0x367d388a,0x29273266,0x29f0335c,0xb473afb6,0xb51bb071,0xb88bb6dc,0xb921b7d1,0xba65b98a,0xbb02ba2d,0xbb96bb15,0xbbeebb99,
0x3ad73b6d,0x3b653bd6,0x39243a12,0x39c03ab1,0x35c73811,0x3697389b,0x29403285,0x2a09337a,0xb488afdc,0xb530b083,0xb89eb6fb,0xb933b7ef,0xba7ab9a0,0xbb13ba3f,0xbba5bb28,0xbbf4bba6,
0x3aeb3b7e,0x3b743bdf,0x39383a28,0x39d23ac3,0x35e13823,0x36b138ab,0x295932a4,0x2a223399,0xb49db001,0xb545b096,0xb8b2b71a,0xb945b807,0xba8fb9b5,0xbb24ba52,0xbbb3bb3b,0xbbf9bbb2,
0x3aff3b8d,0x3b823be6,0x394c3a3c,0x39e43ad4,0x35fb3834,0x36ca38bc,0x297232c2,0x2a3b33b7,0xb4b3b013,0xb55ab0a9,0xb8c5b739,0xb957b815,0xbaa4b9ca,0xbb34ba64,0xbbc0bb4d,0xbbfcbbbd,
0x39b839ba,0x3a973ab5,0x39b339b5,0x3a583a78,0x39af39b1,0x3a153a37,0x39aa39ad,0x39cd39f2,0x39a639a8,0x398239a8,0x39a139a4,0x3933395b,0x399d399f,0x38e03909,0x3999399b,0x388938b5,
0xb979b972,0xb865b832,0xb986b980,0xb8c7b896,0xb994b98d,0xb924b8f6,0xb9a1b99b,0xb97db951,0xb9afb9a8,0xb9d2b9a8,0xb9bcb9b5,0xba21b9fa,0xb9c9b9c3,0xba6bba47,0xb9d6b9d0,0xbab0ba8e,
0xb9f4b9fe,0xbac7bae9,0xb9dfb9e9,0xba7ebaa3,0xb9c9b9d4,0xba2dba56,0xb9b3b9be,0xb9d6ba02,0xb99db9a8,0xb979b9a8,0xb986b992,0xb916b948,0xb970b97b,0xb8adb8e2,0xb958b964,0xb840b877,
0x39373927,0x381a37b7,0x39583948,0x38943858,0x39793969,0x390738ce,0x39993989,0x3974393e,0x39b839a8,0x39da39a8,0x39d639c7,0x3a393a0b,0x39f439e5,0x3a903a65,0x3a113a02,0x3ade3ab8,
0x3a2d3a3f,0x3af43b1a,0x3a093a1b,0x3aa23acc,0x39e339f6,0x3a453a74,0x39bc39d0,0x39df3a13,0x399439a8,0x397039a8,0x396b3980,0x38f83935,0x39413956,0x387a38ba,0x3916392b,0x37e83838,
0xb8f3b8d8,0xb79bb705,0xb929b90e,0xb85fb817,0xb95db943,0xb8eab8a6,0xb990b976,0xb96bb92b,0xb9c0b9a8,0xb9e3b9a8,0xb9f0b9d8,0xba50ba1b,0xba1dba07,0xbab3ba83,0xba49ba33,0xbb0abae0,
0xba64ba7c,0xbb1ebb46,0xba31ba4b,0xbac4baf3,0xb9fcba17,0xba5cba92,0xb9c5b9e1,0xb9e7ba23,0xb98bb9a8,0xb966b9a8,0xb94fb96d,0xb8dbb922,0xb911b930,0xb845b891,0xb8d1b8f1,0xb74eb7ee,
0x38ad3887,0x36ff364e,0x38f838d3,0x382a37ac,0x3941391d,0x38cc387c,0x39863964,0x39623918,0x39c939a8,0x39eb39a8,0x3a0939e9,0x3a673a2b,0x3a453a27,0x3ad53aa0,0x3a7e3a62,0x3b323b05,
0x3b453b6e,0x3bbc3bdd,0x3ae53b17,0x3b573b8f,0x3a733aae,0x3ac73b14,0x39f03a33,0x3a113a71,0x395d39a8,0x393739a8,0x38bc390e,0x384038bf,0x380f3867,0x365f3775,0x36af376a,0x341a3540,
0xb65fb593,0xb389b115,0xb7e8b726,0xb625b4f9,0xb8adb852,0xb830b748,0xb958b905,0xb933b8b5,0xb9f4b9a8,0xba15b9a8,0xba7eba3b,0xbad1ba78,0xbaf4babc,0xbb63bb20,0xbb57bb28,0xbbc6bb9b,
0xbb68bb91,0xbbd0bbed,0xbb04bb39,0xbb6fbba6,0xba89bac9,0xbadbbb2b,0xb9f8ba43,0xba19ba7f,0xb954b9a8,0xb92eb9a8,0xb89eb8fb,0xb820b8ab,0xb7b2b83d,0xb5ebb71b,0xb60eb6e3,0xb2deb4b1,
0x35bc34d5,0x32322f0e,0x377a369e,0x35b13469,0x388e3828,0x380f36ee,0x394f38f1,0x392938a0,0x39fc39a8,0x3a1d39a8,0x3a933a4b,0x3ae53a87,0x3b133ad6,0x3b7a3b36,0x3b783b49,0x3bd93bb1,
0x3b873baf,0x3be13bf8,0x3b213b58,0x3b853bbb,0x3a9e3ae3,0x3aee3b41,0x3a003a52,0x3a213a8e,0x394a39a8,0x392439a8,0x387f38e7,0x37fe3896,0x37423812,0x357636c1,0x356a3659,0x31853420,
0xb517b414,0xb0d7abd9,0xb70ab614,0xb53ab3ae,0xb86fb7f9,0xb7ddb693,0xb946b8dd,0xb91fb88c,0xba04b9a8,0xba25b9a8,0xbaa9ba5a,0xbaf7ba95,0xbb2fbaf0,0xbb90bb4b,0xbb96bb67,0xbbe8bbc4,
0xbba3bbc9,0xbbefbbff,0xbb3dbb74,0xbb9abbcd,0xbab3bafc,0xbb01bb55,0xba09ba62,0xba29ba9c,0xb941b9a8,0xb91bb9a8,0xb85fb8d3,0xb7bdb881,0xb6d2b7cd,0xb4ffb665,0xb4c3b5ce,0xb029b31b,
0x346f32a1,0x2ef52248,0x36993587,0x34c33288,0x385037a1,0x379b3637,0x393c38c9,0x39163877,0x3a0d39a8,0x3a2d39a8,0x3abd3a69,0x3b0a3aa3,0x3b4a3b08,0x3ba33b5f,0x3bb03b82,0x3bf43bd5,
0x3bf83c00,0x3bf93bd4,0x3bac3bdc,0x3be43bfe,0x3b133b69,0x3b543bab,0x3a313aaa,0x3a503ae0,0x391139a8,0x38ea39a8,0x377a386d,0x366b3817,0x34873608,0x313b348d,0x2d9731f4,0xad65291b,
0xac3828b6,0x2ec33365,0xb44bb160,0xb0bea57f,0xb759b5da,0xb648b45d,0xb90cb862,0xb8e5b80d,0xba35b9a8,0xba54b9a8,0xbb1bbab1,0xbb5cbae6,0xbbb5bb72,0xbbe9bbb2,0xbbfcbbe3,0xbbf5bc00,
0xbbfebbfc,0xbbefbbbc,0xbbbdbbe9,0xbbeebc00,0xbb24bb7b,0xbb63bbb9,0xba39bab8,0xba58baed,0xb907b9a8,0xb8e0b9a8,0xb737b858,0xb625b802,0xb40eb5ab,0xb042b42c,0xa9b1b0cb,0x30109a48,
0x25e4ad7e,0xb0beb475,0x33a23036,0x2f8ba3db,0x3715357c,0x360233f7,0x3902384d,0x38db37ee,0x3a3d39a8,0x3a5c39a8,0x3b2c3abf,0x3b6a3af3,0x3bc53b84,0x3bf23bc0,0x3bff3bee,0x3be93c00,
0x3c003bf4,0x3be23ba0,0x3bcc3bf3,0x3bf53bff,0x3b353b8c,0x3b713bc6,0x3a413ac6,0x3a603af9,0x38fd39a8,0x38d639a8,0x36f43842,0x35df37d8,0x3328354c,0x2e913396,0x16482f40,0xb16ca852,
0x251b304e,0x32193534,0xb2adae14,0xad972aac,0xb6d2b51d,0xb5bcb334,0xb8f8b838,0xb8d1b7c2,0xba45b9a8,0xba64b9a8,0xbb3dbacc,0xbb78baff,0xbbd3bb95,0xbbf8bbcb,0xbc00bbf7,0xbbdabbfd,
0xbbfebbe6,0xbbd2bb80,0xbbd9bbfa,0xbbfbbbfb,0xbb45bb9d,0xbb7fbbd1,0xba49bad3,0xba67bb05,0xb8f3b9a8,0xb8ccb9a8,0xb6afb82d,0xb599b7ac,0xb232b4ed,0xac9cb2d2,0x294dace7,0x32c62c83,
0xac06b1db,0xb371b5f1,0x31b62b75,0x2b43adb0,0x368d34bd,0x3576326f,0x38ee3822,0x38c73796,0x3a4d39a8,0x3a6b39a8,0x3b4c3ad9,0x3b853b0b,0x3bdf3ba4,0x3bfd3bd6,0x3bfc3bfd,0x3bc83bf8,
0x3bbd3b5a,0x3b473a99,0x3bfe3bf4,0x3bf93bbe,0x3b8b3bdb,0x3bb83bf7,0x3a6f3b11,0x3a8c3b3e,0x38c139a8,0x389939a8,0x35523780,0x343236cc,0x294d320d,0xad332de2,0xb40eaedc,0xb6a4b408,
0x346336aa,0x36f438b0,0xa6ad3004,0x2e2d3451,0xb52fb1aa,0xb40ead1a,0xb8bcb76a,0xb894b6b5,0xba73b9a8,0xba90b9a8,0xbb92bb17,0xbbbdbb43,0xbbffbbe0,0xbbf6bbf9,0xbbb2bbf0,0xbb35bbb4,
0xbba5bb30,0xbb21ba5e,0xbc00bbeb,0xbbf3bbaa,0xbb98bbe4,0xbbc2bbfb,0xba76bb1d,0xba93bb49,0xb8b7b9a8,0xb88eb9a8,0xb50bb753,0xb3d3b69e,0xa17fb147,0x2f27ac51,0x34b73099,0x37423499,
0xb50bb75e,0xb790b900,0x9cb6b12e,0xb010b4e1,0x34e730e4,0x33892b11,0x38b2373d,0x38893687,0x3a7a39a8,0x3a9739a8,0x3b9e3b22,0x3bc63b4e,0x3c003be8,0x3bef3bfd,0x3b983be5,0x3b0d3b9e,
0x3b893b02,0x3af73a1f,0x3c003bdf,0x3beb3b93,0x3ba33bec,0x3bcb3bfe,0x3a7e3b28,0x3a9b3b53,0x38ad39a8,0x388439a8,0x34c33726,0x33403670,0xa51b3080,0xb08d297f,0xb55eb1c3,0xb7ddb529,
0x35b13807,0x3815394d,0x28843257,0x31093570,0xb49fb01d,0xb2f7a7da,0xb8a8b710,0xb87fb659,0xba81b9a8,0xba9eb9a8,0xbba9bb2e,0xbbcfbb58,0xbbffbbef,0xbbe6bbff,0xbb7abbd7,0xbae1bb86,
0xbb6abad0,0xbacbb9dc,0xbbfdbbd0,0xbbe1bb79,0xbbaebbf2,0xbbd3bc00,0xba85bb33,0xbaa2bb5d,0xb8a3b9a8,0xb87ab9a8,0xb47bb6f9,0xb2adb642,0x2a7aaf72,0x3185a4b6,0x360232ea,0x383a35b6,
0xb654b85d,0xb85fb996,0xac38b37d,0xb201b5fd,0x34572eaa,0x32631e48,0x389e36e3,0x3874362b,0x3a8939a8,0x3aa539a8,0x3bb33b39,0x3bd73b62,0x3bfc3bf5,0x3bdc3c00,0x3b593bc7,0x3ab33b6b,
0x39b739b9,0x3a883aa6,0x39b239b4,0x3a483a68,0x39ae39b0,0x3a033a26,0x39a939ab,0x39bb39e0,0x39a539a7,0x396e3995,0x39a039a3,0x391e3947,0x399c399e,0x38ca38f5,0x3997399a,0x3873389f,
0xb97cb975,0xb87eb84c,0xb98ab983,0xb8deb8ae,0xb997b991,0xb93bb90d,0xb9a5b99e,0xb993b967,0xb9b2b9ab,0xb9e6b9bd,0xb9bfb9b9,0xba34ba0e,0xb9ccb9c6,0xba7dba59,0xb9d9b9d3,0xbac0ba9f,
0xb9efb9f9,0xbab6bad9,0xb9d9b9e4,0xba6aba91,0xb9c4b9cf,0xba18ba42,0xb9aeb9b9,0xb9bfb9ec,0xb997b9a3,0xb961b991,0xb981b98c,0xb8fcb92f,0xb96ab975,0xb892b8c8,0xb953b95e,0xb824b85c,
0x3940392f,0x383937f6,0x39613950,0x38b13876,0x39813971,0x392338eb,0x39a03991,0x398e395a,0x39bf39b0,0x39f339c1,0x39de39cf,0x3a4f3a22,0x39fb39ec,0x3aa43a7b,0x3a183a0a,0x3af03acb,
0x3a243a36,0x3ae13b07,0x39ff3a12,0x3a8b3ab7,0x39d939ec,0x3a2c3a5d,0x39b239c6,0x39c439f9,0x398a399e,0x3953398c,0x39613975,0x38d93917,0x3936394b,0x3859389a,0x390b3921,0x37a43816,
0xb901b8e6,0xb7e6b750,0xb936b91c,0xb883b83c,0xb96ab950,0xb90bb8c8,0xb99cb983,0xb98ab94b,0xb9ccb9b4,0xb9ffb9c6,0xb9fbb9e4,0xba6aba36,0xba28ba12,0xbacaba9b,0xba53ba3e,0xbb1dbaf5,
0xba57ba70,0xbb09bb33,0xba24ba3e,0xbaabbadc,0xb9efba0a,0xba40ba77,0xb9b7b9d3,0xb9c8ba05,0xb97cb99a,0xb944b988,0xb940b95e,0xb8b6b8fe,0xb901b921,0xb81eb86b,0xb8c0b8e1,0xb6fcb79e,
0x38c0389a,0x375636a7,0x390b38e6,0x38543800,0x3953392f,0x38f238a4,0x39973975,0x3985393d,0x39d939b9,0x3a0c39ca,0x3a1839f9,0x3a843a4a,0x3a533a36,0x3aed3abb,0x3a8b3a70,0x3b473b1c,
0x3b2e3b5a,0x3ba63bce,0x3aca3afe,0x3b373b74,0x3a533a91,0x3a9d3aef,0x39cc3a12,0x39de3a42,0x39363983,0x38fc3971,0x389238e6,0x37fb3880,0x37c5383c,0x35d136eb,0x3651370d,0x330934ae,
0xb6c3b5fa,0xb460b251,0xb824b788,0xb6b8b590,0xb8d9b880,0xb873b7d5,0xb981b92f,0xb96eb8f5,0xba18b9cf,0xba48b9e0,0xba9dba5d,0xbafabaa6,0xbb0fbad9,0xbb80bb43,0xbb6cbb40,0xbbd8bbb2,
0xbb51bb7d,0xbbbdbbe0,0xbae7bb1f,0xbb4ebb8c,0xba66baa9,0xbaafbb04,0xb9d1ba1e,0xb9e2ba4e,0xb928b97e,0xb8edb96c,0xb86eb8cd,0xb7afb866,0xb74bb80b,0xb54fb684,0xb5a2b679,0xb197b411,
0x362e3549,0x338330de,0x37e6370d,0x3651350e,0x38c0385c,0x38593788,0x397c3921,0x396a38e6,0x3a2439d3,0x3a5339e4,0x3ab63a70,0x3b0f3ab7,0x3b2e3af5,0x3b973b5a,0x3b8d3b61,0x3be83bc7,
0x3b703b9c,0x3bd03bef,0x3b033b3d,0x3b653ba2,0x3a793ac1,0x3ac03b19,0x39d53a2a,0x39e63a59,0x3919397a,0x38de3967,0x384938b4,0x3761384c,0x36cf37b4,0x34cc361d,0x34f035e2,0x302332e4,
0xb596b496,0xb244aecf,0xb783b690,0xb5e8b48a,0xb8a7b836,0xb83eb73a,0xb978b912,0xb965b8d7,0xba30b9d7,0xba5fb9e8,0xbacdba82,0xbb23bac8,0xbb4cbb10,0xbbacbb6f,0xbbaabb7f,0xbbf4bbd8,
0xbb8dbbb7,0xbbe0bbf9,0xbb1dbb5a,0xbb7abbb5,0xba8bbad9,0xbad0bb2d,0xb9d9ba36,0xb9eaba65,0xb90bb975,0xb8cfb963,0xb824b89a,0xb713b831,0xb651b750,0xb447b5b3,0xb43bb549,0xad58b1a4,
0x34fc33c0,0x31032bc0,0x371e3611,0x357e3405,0x388d3811,0x382436eb,0x39733903,0x396138c8,0x3a3c39db,0x3a6a39ec,0x3ae43a94,0x3b373ad9,0x3b673b2a,0x3bbe3b83,0x3bc33b9a,0x3bfc3be7,
0x3bed3bff,0x3bff3bea,0x3b8d3bc7,0x3bcc3bf5,0x3ae13b40,0x3b1d3b83,0x39ef3a70,0x39ff3a9b,0x38c0395e,0x3883394b,0x36c33816,0x357e3750,0x33833549,0x2e84332e,0x28cf3061,0xb0aca5b2,
0xaf7ea376,0x29663166,0xb514b2fd,0xb2bfad71,0xb809b69b,0xb734b555,0xb95cb8b9,0xb949b87b,0xba75b9f1,0xbaa1ba01,0xbb49bae9,0xbb8bbb25,0xbbcfbb96,0xbbf9bbd2,0xbc00bbf2,0xbbe3bbfe,
0xbbf6bc00,0xbbfcbbda,0xbb9fbbd6,0xbbd8bbfb,0xbaf0bb52,0xbb2cbb92,0xb9f3ba7b,0xba03baa6,0xb8b1b95a,0xb873b947,0xb673b7f6,0xb52cb718,0xb276b4de,0xac5eb251,0x2052ae39,0x321f2bf2,
0x2cf4a806,0xad3fb2d8,0x34a831ee,0x31e22a93,0x37db364b,0x36fc3502,0x395738a9,0x3944386b,0x3a8039f5,0x3aab3a05,0x3b5b3af8,0x3b993b33,0x3bdd3ba7,0x3bfd3bdd,0x3bff3bfa,0x3bd13bf9,
0x3bfd3bfd,0x3bf53bc6,0x3baf3be3,0x3be23bff,0x3b003b64,0x3b393ba0,0x39f73a86,0x3a083ab0,0x38a23955,0x38633942,0x362237bf,0x34d836e0,0x31663472,0x286b3172,0xaaf82b5c,0xb390ae84,
0xa8cf2cf4,0x2fc93423,0xb43bb0de,0xb103a484,0xb7a4b5fa,0xb6c3b4ae,0xb953b89a,0xb940b85c,0xba8bb9f9,0xbab6ba0a,0xbb6cbb07,0xbba6bb40,0xbbe8bbb7,0xbc00bbe7,0xbbfabbff,0xbbbabbf1,
0xbc00bbf6,0xbbebbbae,0xbbbebbed,0xbbebbc00,0xbb0fbb74,0xbb47bbad,0xb9fbba91,0xba0cbabb,0xb892b950,0xb854b93d,0xb5d1b788,0xb484b6a7,0xb055b405,0x9248b093,0x2e6ba484,0x347e3086,
0x98b6afe2,0xb128b4d8,0x339c2f97,0x3023a420,0x376c35a8,0x368a345a,0x394e388b,0x393b384c,0x3a9639fd,0x3ac03a0e,0x3b7c3b16,0x3bb33b4d,0x3bf23bc5,0x3c003bef,0x3bf03c00,0x3ba03be5,
0x3bde3b91,0x3b8a3af7,0x3bf23bff,0x3c003be3,0x3b533bb9,0x3b823bdf,0x3a103ac5,0x3a203aec,0x38443939,0x38033925,0x342f366d,0x31b03584,0xa8392f65,0xb15a1d7f,0xb531b1c9,0xb7e0b55b,
0x3269358a,0x35a83819,0xae842a61,0x205231e2,0xb651b405,0xb567b15a,0xb936b83c,0xb923b7f6,0xbacaba12,0xbaf0ba22,0xbbbebb5a,0xbbe3bb88,0xbbfdbbf5,0xbbddbc00,0xbb81bbd6,0xbadfbb7c,
0xbbcebb70,0xbb6dbac6,0xbbf8bbfb,0xbbffbbd6,0xbb60bbc4,0xbb8dbbe7,0xba14bacf,0xba24baf5,0xb834b934,0xb7e6b921,0xb3b4b634,0xb103b549,0x2c44ada3,0x326925b2,0x35e23309,0x384135f4,
0xb3a8b63a,0xb63fb869,0x2cc2ad58,0xa89db2f0,0x3617335f,0x352c30ac,0x3931382c,0x391e37d5,0x3ad43a16,0x3afa3a26,0x3bc93b66,0x3bea3b92,0x3bf93bfa,0x3bcf3bff,0x3b5f3bc5,0x3aad3b5d,
0x3bba3b4c,0x3b4d3a93,0x3bfc3bf6,0x3bfd3bc7,0x3b6c3bce,0x3b973bed,0x3a183ad9,0x3a283afe,0x3824392f,0x37c5391c,0x330935fa,0x3055350e,0xae6b2bc0,0xb377aa61,0xb690b423,0xb890b68a,
0x347236e5,0x36d438b6,0xa9fd2f7e,0x2c1233fd,0xb5dcb2b3,0xb4f0affb,0xb92db81c,0xb919b7b4,0xbaddba1a,0xbb03ba2a,0xbbd3bb72,0xbbf0bb9c,0xbbf2bbfe,0xbbbfbbfc,0xbb38bbaf,0xba77bb3c,
0xbba4bb23,0xbb2aba5b,0xbbffbbee,0xbbfabbb6,0xbb77bbd7,0xbba1bbf3,0xba1cbae2,0xba2cbb07,0xb813b92a,0xb7a4b917,0xb25db5bf,0xaf4cb4d2,0x3048a839,0x34412cf4,0x373a34c0,0x38dc371e,
0xb50eb78e,0xb767b901,0x24e9b0d1,0xadd5b484,0x35a23207,0x34b42e9d,0x3928380b,0x39143793,0x3ae73a1e,0x3b0c3a2e,0x3bdb3b7d,0x3bf53ba6,0x3be93c00,0x3bad3bf7,0x3b0d3b97,0x3a3e3b18,
0xb999b996,0xb889b85d,0xb99db99b,0xb8e0b8b5,0xb9a1b99f,0xb933b909,0xb9a6b9a4,0xb982b95b,0xb9aab9a8,0xb9cdb9a8,0xb9afb9ad,0xba15b9f2,0xb9b3b9b1,0xba58ba37,0xb9b8b9b5,0xba97ba78,
0xb9d6b9dc,0xbab0bad0,0xb9c9b9d0,0xba6bba8e,0xb9bcb9c3,0xba21ba47,0xb9afb9b5,0xb9d2b9fa,0xb9a1b9a8,0xb97db9a8,0xb994b99b,0xb924b951,0xb986b98d,0xb8c7b8f6,0xb979b980,0xb865b896,
0x3958394d,0x38403807,0x39703964,0x38ad3877,0x3986397b,0x391638e2,0x399d3992,0x39793948,0x39b339a8,0x39d639a8,0x39c939be,0x3a2d3a02,0x39df39d4,0x3a7e3a56,0x39f439e9,0x3ac73aa3,
0x3a113a1f,0x3ade3b02,0x39f43a02,0x3a903ab8,0x39d639e5,0x3a393a65,0x39b839c7,0x39da3a0b,0x399939a8,0x397439a8,0x39793989,0x3907393e,0x39583969,0x389438ce,0x39373948,0x381a3858,
0xb916b900,0xb7e8b75e,0xb941b92b,0xb87ab838,0xb96bb956,0xb8f8b8ba,0xb994b980,0xb970b935,0xb9bcb9a8,0xb9dfb9a8,0xb9e3b9d0,0xba45ba13,0xba09b9f6,0xbaa2ba74,0xba2dba1b,0xbaf4bacc,
0xba49ba5e,0xbb0abb30,0xba1dba33,0xbab3bae0,0xb9f0ba07,0xba50ba83,0xb9c0b9d8,0xb9e3ba1b,0xb990b9a8,0xb96bb9a8,0xb95db976,0xb8eab92b,0xb929b943,0xb85fb8a6,0xb8f3b90e,0xb79bb817,
0x38d138b0,0x374e36aa,0x391138f1,0x384537ee,0x394f3930,0x38db3891,0x398b396d,0x39663922,0x39c539a8,0x39e739a8,0x39fc39e1,0x3a5c3a23,0x3a313a17,0x3ac43a92,0x3a643a4b,0x3b1e3af3,
0x3a7e3a99,0x3b323b5a,0x3a453a62,0x3ad53b05,0x3a093a27,0x3a673aa0,0x39c939e9,0x39eb3a2b,0x398639a8,0x396239a8,0x39413964,0x38cc3918,0x38f8391d,0x382a387c,0x38ad38d3,0x36ff37ac,
0xb6afb5f1,0xb41ab1db,0xb80fb76a,0xb65fb540,0xb8bcb867,0xb840b775,0xb95db90e,0xb937b8bf,0xb9f0b9a8,0xba11b9a8,0xba73ba33,0xbac7ba71,0xbae5baae,0xbb57bb14,0xbb45bb17,0xbbbcbb8f,
0xbb57bb80,0xbbc6bbe6,0xbaf4bb28,0xbb63bb9b,0xba7ebabc,0xbad1bb20,0xb9f4ba3b,0xba15ba78,0xb958b9a8,0xb933b9a8,0xb8adb905,0xb830b8b5,0xb7e8b852,0xb625b748,0xb65fb726,0xb389b4f9,
0x360e3534,0x32de304e,0x37b236e3,0x35eb34b1,0x389e383d,0x3820371b,0x395438fb,0x392e38ab,0x39f839a8,0x3a1939a8,0x3a893a43,0x3adb3a7f,0x3b043ac9,0x3b6f3b2b,0x3b683b39,0x3bd03ba6,
0x3b783ba0,0x3bd93bf4,0x3b133b49,0x3b7a3bb1,0x3a933ad6,0x3ae53b36,0x39fc3a4b,0x3a1d3a87,0x394f39a8,0x392939a8,0x388e38f1,0x380f38a0,0x377a3828,0x35b136ee,0x35bc369e,0x32323469,
0xb56ab475,0xb185ad7e,0xb742b659,0xb576b420,0xb87fb812,0xb7feb6c1,0xb94ab8e7,0xb924b896,0xba00b9a8,0xba21b9a8,0xba9eba52,0xbaeeba8e,0xbb21bae3,0xbb85bb41,0xbb87bb58,0xbbe1bbbb,
0xbb96bbbc,0xbbe8bbfc,0xbb2fbb67,0xbb90bbc4,0xbaa9baf0,0xbaf7bb4b,0xba04ba5a,0xba25ba95,0xb946b9a8,0xb91fb9a8,0xb86fb8dd,0xb7ddb88c,0xb70ab7f9,0xb53ab693,0xb517b614,0xb0d7b3ae,
0x34c33365,0x302928b6,0x36d235ce,0x34ff331b,0x385f37cd,0x37bd3665,0x394138d3,0x391b3881,0x3a0939a8,0x3a2939a8,0x3ab33a62,0x3b013a9c,0x3b3d3afc,0x3b9a3b55,0x3ba33b74,0x3bef3bcd,
0x3bb03bd4,0x3bf43c00,0x3b4a3b82,0x3ba33bd5,0x3abd3b08,0x3b0a3b5f,0x3a0d3a69,0x3a2d3aa3,0x393c39a8,0x391639a8,0x385038c9,0x379b3877,0x369937a1,0x34c33637,0x346f3587,0x2ef53288,
0xad972248,0x2d6532a1,0xb487b1f4,0xb13ba91b,0xb77ab608,0xb66bb48d,0xb911b86d,0xb8eab817,0xba31b9a8,0xba50b9a8,0xbb13baaa,0xbb54bae0,0xbbacbb69,0xbbe4bbab,0xbbf8bbdc,0xbbf9bbfe,
0xbbfcbbff,0xbbf5bbc9,0xbbb5bbe3,0xbbe9bc00,0xbb1bbb72,0xbb5cbbb2,0xba35bab1,0xba54bae6,0xb90cb9a8,0xb8e5b9a8,0xb759b862,0xb648b80d,0xb44bb5da,0xb0beb45d,0xac38b160,0x2ec3a57f,
0x29b1abd9,0xb010b414,0x340e30cb,0x30421a48,0x373735ab,0x3625342c,0x39073858,0x38e03802,0x3a3939a8,0x3a5839a8,0x3b243ab8,0x3b633aed,0x3bbd3b7b,0x3bee3bb9,0x3bfe3be9,0x3bef3c00,
0x3bff3bf8,0x3be93baf,0x3bc53bee,0x3bf23c00,0x3b2c3b84,0x3b6a3bc0,0x3a3d3abf,0x3a5c3af3,0x390239a8,0x38db39a8,0x3715384d,0x360237ee,0x33a2357c,0x2f8b33f7,0x25e43036,0xb0bea3db,
0x96482f0e,0x316c34d5,0xb328af40,0xae912852,0xb6f4b54c,0xb5dfb396,0xb8fdb842,0xb8d6b7d8,0xba41b9a8,0xba60b9a8,0xbb35bac6,0xbb71baf9,0xbbccbb8c,0xbbf5bbc6,0xbc00bbf3,0xbbe2bbff,
0xbc00bbed,0xbbdabb91,0xbbd3bbf7,0xbbf8bbfd,0xbb3dbb95,0xbb78bbcb,0xba45bacc,0xba64baff,0xb8f8b9a8,0xb8d1b9a8,0xb6d2b838,0xb5bcb7c2,0xb2adb51d,0xad97b334,0x251bae14,0x32192aac,
0xa94db115,0xb2c6b593,0x32322ce7,0x2c9cac83,0x36af34ed,0x359932d2,0x38f3382d,0x38cc37ac,0x3a4939a8,0x3a6739a8,0x3b453ad3,0x3b7f3b05,0x3bd93b9d,0x3bfb3bd1,0x3bfe3bfa,0x3bd23bfb,
0x3bfc3bdd,0x3bc83b6e,0x3bdf3bfd,0x3bfd3bf8,0x3b4c3ba4,0x3b853bd6,0x3a4d3ad9,0x3a6b3b0b,0x38ee39a8,0x38c739a8,0x368d3822,0x35763796,0x31b634bd,0x2b43326f,0xac062b75,0xb371adb0,
0x340e364e,0x36a43887,0xa94d2edc,0x2d333408,0xb552b20d,0xb432ade2,0xb8c1b780,0xb899b6cc,0xba6fb9a8,0xba8cb9a8,0xbb8bbb11,0xbbb8bb3e,0xbbfebbdb,0xbbf9bbf7,0xbbbdbbf4,0xbb47bbbe,
0xbbb2bb46,0xbb35ba7c,0xbbffbbf0,0xbbf6bbb4,0xbb92bbe0,0xbbbdbbf9,0xba73bb17,0xba90bb43,0xb8bcb9a8,0xb894b9a8,0xb52fb76a,0xb40eb6b5,0xa6adb1aa,0x2e2dad1a,0x34633004,0x36f43451,
0xb4b7b705,0xb742b8d8,0x217fb099,0xaf27b499,0x350b3147,0x33d32c51,0x38b73753,0x388e369e,0x3a7639a8,0x3a9339a8,0x3b983b1d,0x3bc23b49,0x3c003be4,0x3bf33bfb,0x3ba53beb,0x3b213baa,
0x3b983b1a,0x3b0d3a3f,0x3c003be5,0x3bef3b9e,0x3b9e3be8,0x3bc63bfd,0x3a7a3b22,0x3a973b4e,0x38b239a8,0x388939a8,0x34e7373d,0x33893687,0x9cb630e4,0xb0102b11,0xb50bb12e,0xb790b4e1,
0x355e37b7,0x37dd3927,0x251b31c3,0x308d3529,0xb4c3b080,0xb340a97f,0xb8adb726,0xb884b670,0xba7eb9a8,0xba9bb9a8,0xbba3bb28,0xbbcbbb53,0xbc00bbec,0xbbebbbfe,0xbb89bbdf,0xbaf7bb93,
0xbb7abae9,0xbae1b9fe,0xbbffbbd7,0xbbe6bb86,0xbba9bbef,0xbbcfbbff,0xba81bb2e,0xba9ebb58,0xb8a8b9a8,0xb87fb9a8,0xb49fb710,0xb2f7b659,0x2884b01d,0x3109a7da,0x35b13257,0x38153570,
0xb602b832,0xb83ab972,0xaa7ab2ea,0xb185b5b6,0x347b2f72,0x32ad24b6,0x38a336f9,0x387a3642,0x3a8539a8,0x3aa239a8,0x3bae3b33,0x3bd33b5d,0x3bfd3bf2,0x3be13c00,0x3b6a3bd0,0x3acb3b79,
0x3b593ab5,0x3ab339ba,0x3bfc3bc7,0x3bdc3b6b,0x3bb33bf5,0x3bd73c00,0x3a893b39,0x3aa53b62,0x389e39a8,0x387439a8,0x345736e3,0x3263362b,0xac382eaa,0xb2011e48,0xb654b37d,0xb85fb5fd,
0xb99ab997,0xb89fb873,0xb99eb99c,0xb8f5b8ca,0xb9a3b9a0,0xb947b91e,0xb9a7b9a5,0xb995b96e,0xb9abb9a9,0xb9e0b9bb,0xb9b0b9ae,0xba26ba03,0xb9b4b9b2,0xba68ba48,0xb9b9b9b7,0xbaa6ba88,
0xb9d3b9d9,0xba9fbac0,0xb9c6b9cc,0xba59ba7d,0xb9b9b9bf,0xba0eba34,0xb9abb9b2,0xb9bdb9e6,0xb99eb9a5,0xb967b993,0xb991b997,0xb90db93b,0xb983b98a,0xb8aeb8de,0xb975b97c,0xb84cb87e,
0x395e3953,0x385c3824,0x3975396a,0x38c83892,0x398c3981,0x392f38fc,0x39a33997,0x39913961,0x39b939ae,0x39ec39bf,0x39cf39c4,0x3a423a18,0x39e439d9,0x3a913a6a,0x39f939ef,0x3ad93ab6,
0x3a0a3a18,0x3acb3af0,0x39ec39fb,0x3a7b3aa4,0x39cf39de,0x3a223a4f,0x39b039bf,0x39c139f3,0x399139a0,0x395a398e,0x39713981,0x38eb3923,0x39503961,0x387638b1,0x392f3940,0x37f63839,
0xb921b90b,0xb816b7a4,0xb94bb936,0xb89ab859,0xb975b961,0xb917b8d9,0xb99eb98a,0xb98cb953,0xb9c6b9b2,0xb9f9b9c4,0xb9ecb9d9,0xba5dba2c,0xba12b9ff,0xbab7ba8b,0xba36ba24,0xbb07bae1,
0xba3eba53,0xbaf5bb1d,0xba12ba28,0xba9bbaca,0xb9e4b9fb,0xba36ba6a,0xb9b4b9cc,0xb9c6b9ff,0xb983b99c,0xb94bb98a,0xb950b96a,0xb8c8b90b,0xb91cb936,0xb83cb883,0xb8e6b901,0xb750b7e6,
0x38e138c0,0x379e36fc,0x39213901,0x386b381e,0x395e3940,0x38fe38b6,0x399a397c,0x39883944,0x39d339b7,0x3a0539c8,0x3a0a39ef,0x3a773a40,0x3a3e3a24,0x3adc3aab,0x3a703a57,0x3b333b09,
0x3a703a8b,0x3b1c3b47,0x3a363a53,0x3abb3aed,0x39f93a18,0x3a4a3a84,0x39b939d9,0x39ca3a0c,0x39753997,0x393d3985,0x392f3953,0x38a438f2,0x38e6390b,0x38003854,0x389a38c0,0x36a73756,
0xb70db651,0xb4aeb309,0xb83cb7c5,0xb6ebb5d1,0xb8e6b892,0xb880b7fb,0xb983b936,0xb971b8fc,0xba12b9cc,0xba42b9de,0xba91ba53,0xbaefba9d,0xbafebaca,0xbb74bb37,0xbb5abb2e,0xbbcebba6,
0xbb40bb6c,0xbbb2bbd8,0xbad9bb0f,0xbb43bb80,0xba5dba9d,0xbaa6bafa,0xb9cfba18,0xb9e0ba48,0xb92fb981,0xb8f5b96e,0xb880b8d9,0xb7d5b873,0xb788b824,0xb590b6b8,0xb5fab6c3,0xb251b460,
0x367935a2,0x34113197,0x380b374b,0x3684354f,0x38cd386e,0x386637af,0x397e3928,0x396c38ed,0x3a1e39d1,0x3a4e39e2,0x3aa93a66,0x3b043aaf,0x3b1f3ae7,0x3b8c3b4e,0x3b7d3b51,0x3be03bbd,
0x3b613b8d,0x3bc73be8,0x3af53b2e,0x3b5a3b97,0x3a703ab6,0x3ab73b0f,0x39d33a24,0x39e43a53,0x3921397c,0x38e6396a,0x385c38c0,0x37883859,0x370d37e6,0x350e3651,0x3549362e,0x30de3383,
0xb5e2b4f0,0xb2e4b023,0xb7b4b6cf,0xb61db4cc,0xb8b4b849,0xb84cb761,0xb97ab919,0xb967b8de,0xba2ab9d5,0xba59b9e6,0xbac1ba79,0xbb19bac0,0xbb3dbb03,0xbba2bb65,0xbb9cbb70,0xbbefbbd0,
0xbb7fbbaa,0xbbd8bbf4,0xbb10bb4c,0xbb6fbbac,0xba82bacd,0xbac8bb23,0xb9d7ba30,0xb9e8ba5f,0xb912b978,0xb8d7b965,0xb836b8a7,0xb73ab83e,0xb690b783,0xb48ab5e8,0xb496b596,0xaecfb244,
0x3549343b,0x31a42d58,0x37503651,0x35b33447,0x389a3824,0x38313713,0x3975390b,0x396338cf,0x3a3639d9,0x3a6539ea,0x3ad93a8b,0x3b2d3ad0,0x3b5a3b1d,0x3bb53b7a,0x3bb73b8d,0x3bf93be0,
0x3b9a3bc3,0x3be73bfc,0x3b2a3b67,0x3b833bbe,0x3a943ae4,0x3ad93b37,0x39db3a3c,0x39ec3a6a,0x39033973,0x38c83961,0x3811388d,0x36eb3824,0x3611371e,0x3405357e,0x33c034fc,0x2bc03103,
0xb061a8cf,0x25b230ac,0xb549b383,0xb32eae84,0xb816b6c3,0xb750b57e,0xb95eb8c0,0xb94bb883,0xba70b9ef,0xba9bb9ff,0xbb40bae1,0xbb83bb1d,0xbbc7bb8d,0xbbf5bbcc,0xbbffbbed,0xbbeabbff,
0xbbf2bc00,0xbbfebbe3,0xbb96bbcf,0xbbd2bbf9,0xbae9bb49,0xbb25bb8b,0xb9f1ba75,0xba01baa1,0xb8b9b95c,0xb87bb949,0xb69bb809,0xb555b734,0xb2fdb514,0xad71b2bf,0xa376af7e,0x31662966,
0x2e39a052,0xabf2b21f,0x34de3276,0x32512c5e,0x37f63673,0x3718352c,0x395a38b1,0x39473873,0x3a7b39f3,0x3aa63a03,0x3b523af0,0x3b923b2c,0x3bd63b9f,0x3bfb3bd8,0x3c003bf6,0x3bda3bfc,
0x3bfa3bff,0x3bf93bd1,0x3ba73bdd,0x3bdd3bfd,0x3af83b5b,0x3b333b99,0x39f53a80,0x3a053aab,0x38a93957,0x386b3944,0x364b37db,0x350236fc,0x31ee34a8,0x2a9331e2,0xa8062cf4,0xb2d8ad3f,
0xab5c2af8,0x2e843390,0xb472b166,0xb172a86b,0xb7bfb622,0xb6e0b4d8,0xb955b8a2,0xb942b863,0xba86b9f7,0xbab0ba08,0xbb64bb00,0xbba0bb39,0xbbe3bbaf,0xbbffbbe2,0xbbfdbbfd,0xbbc6bbf5,
0xbbffbbfa,0xbbf1bbba,0xbbb7bbe8,0xbbe7bc00,0xbb07bb6c,0xbb40bba6,0xb9f9ba8b,0xba0abab6,0xb89ab953,0xb85cb940,0xb5fab7a4,0xb4aeb6c3,0xb0deb43b,0xa484b103,0x2cf4a8cf,0x34232fc9,
0x2484ae6b,0xb086b47e,0x34053055,0x30931248,0x378835d1,0x36a73484,0x39503892,0x393d3854,0x3a9139fb,0x3abb3a0c,0x3b743b0f,0x3bad3b47,0x3bed3bbe,0x3c003beb,0x3bf63c00,0x3bae3beb,
0x3c003bf0,0x3be53ba0,0x3bc53bf2,0x3bef3c00,0x3b163b7c,0x3b4d3bb3,0x39fd3a96,0x3a0e3ac0,0x388b394e,0x384c393b,0x35a8376c,0x345a368a,0x2f97339c,0xa4203023,0xafe298b6,0xb4d8b128,
0x31c93531,0x355b37e0,0xaf652839,0x9d7f315a,0xb66db42f,0xb584b1b0,0xb939b844,0xb925b803,0xbac5ba10,0xbaecba20,0xbbb9bb53,0xbbdfbb82,0xbbffbbf2,0xbbe3bc00,0xbb91bbde,0xbaf7bb8a,
0xbbd6bb81,0xbb7cbadf,0xbbf5bbfd,0xbc00bbdd,0xbb5abbbe,0xbb88bbe3,0xba12baca,0xba22baf0,0xb83cb936,0xb7f6b923,0xb405b651,0xb15ab567,0x2a61ae84,0x31e22052,0x358a3269,0x381935a8,
0xb309b5e2,0xb5f4b841,0x2da3ac44,0xa5b2b269,0x363433b4,0x35493103,0x39343834,0x392137e6,0x3acf3a14,0x3af53a24,0x3bc43b60,0x3be73b8d,0x3bfb3bf8,0x3bd63bff,0x3b703bce,0x3ac63b6d,
0x3bc53b5f,0x3b5d3aad,0x3bfa3bf9,0x3bff3bcf,0x3b663bc9,0x3b923bea,0x3a163ad4,0x3a263afa,0x382c3931,0x37d5391e,0x335f3617,0x30ac352c,0xad582cc2,0xb2f0a89d,0xb63ab3a8,0xb869b63f,
0x34233690,0x368a3890,0xabc02e6b,0x2a613377,0xb5fab309,0xb50eb055,0xb92fb824,0xb91cb7c5,0xbad9ba18,0xbafeba28,0xbbcebb6c,0xbbedbb97,0xbbf6bbfc,0xbbc7bbfd,0xbb4cbbba,0xba93bb4d,
0xbbafbb38,0xbb3cba77,0xbbfebbf2,0xbbfcbbbf,0xbb72bbd3,0xbb9cbbf0,0xba1abadd,0xba2abb03,0xb81cb92d,0xb7b4b919,0xb2b3b5dc,0xaffbb4f0,0x2f7ea9fd,0x33fd2c12,0x36e53472,0x38b636d4,
0xb4c0b73a,0xb71eb8dc,0x2839b048,0xacf4b441,0x35bf325d,0x34d22f4c,0x392a3813,0x391737a4,0x3ae23a1c,0x3b073a2c,0x3bd73b77,0x3bf33ba1,0x3bee3bff,0x3bb63bfa,0x3b233ba4,0x3a5b3b2a,
0x3b973b0d,0x3b183a3e,0x3c003be9,0x3bf73bad,0x3b7d3bdb,0x3ba63bf5,0x3a1e3ae7,0x3a2e3b0c,0x380b3928,0x37933914,0x320735a2,0x2e9d34b4,0xb0d124e9,0xb484add5,0xb78eb50e,0xb901b767,
0xb97239ba,0x39dc3996,0xb8323ab5,0x3ad0385d,0x3927b9fe,0xba1fb94d,0x37b7bae9,0xbb02b807,0xb8d83a3f,0x3a5e3900,0xb7053b1a,0x3b30375e,0x3887ba7c,0xba99b8b0,0x364ebb46,0xbb5ab6aa,
0xb90039dc,0x3a3f3972,0xad7e3be6,0x3bf83115,0x3807ba99,0xbae9b887,0xabd9bc00,0xbbfca248,0xb5f13b30,0x3b6e3705,0x32a13bed,0x3bd4b04e,0x3365bba0,0xbbc9b4d5,0xb593bbaf,0xbb803475,
0xb88739fe,0x3a99394d,0x35f13bbc,0x3b6eb414,0x3593bb1a,0xbb80b75e,0xb8b0bb02,0xba7c37b7,0xaf0e3bc9,0x3bf43365,0x3a1f39dc,0x3927b972,0xb04ebc00,0xbbed2248,0xbb30b85d,0xb7053ab5,
0xb8073a1f,0x3ae93927,0x39fe3a3f,0x394db900,0x31dbbb80,0xbbddb593,0xbb6eb832,0xb5f13ad0,0x31153c00,0x3be62248,0x3bff32a1,0x28b6bbd4,0xb7b7bb91,0xbb023534,0xbba0304e,0x34d53bed,
0xb7053a3f,0x3b303900,0x3bbc375e,0x3414bb1a,0x2248bbc9,0xbc00b365,0xbbdda8b6,0x31db3bff,0x36aa3bd4,0x3b46b2a1,0x3a7cb64e,0xb8b0bb5a,0xba1fba5e,0xb92738d8,0xb7b739fe,0x3b02394d,
0xb5f13a5e,0x3b6e38d8,0x3bd42bd9,0xb2a1bbfc,0xb115bbf4,0xbbe6af0e,0xb9dc375e,0x39723b1a,0x39273b46,0x3a1fb6aa,0x3475bad0,0xbbafb832,0xbb91b887,0xb5343a99,0x34143c00,0x3bbc2248,
0xb4d53a7c,0x3ba038b0,0x3a3fb593,0xb900bb80,0xb534bc00,0xbb912248,0xb4143ab5,0x3bbc385d,0x3a993a5e,0x3887b8d8,0xb5f1bbfc,0xbb6e2bd9,0xbbffb475,0x28b63baf,0x3ad03a1f,0x3832b927,
0xb3653a99,0x3bc93887,0x36aab996,0xbb46b9ba,0xb7b7bbed,0xbb02304e,0x34d53bfc,0x3ba02bd9,0x3b913927,0x3534ba1f,0xbae9ba3f,0xb8073900,0xbb5a28b6,0x364e3bff,0x3bd43115,0xb2a1bbe6,
0xb1153ab5,0x3be6385d,0xa8b6bb6e,0xbbffb5f1,0xb900bbbc,0xba3f3414,0x3a1f3b30,0x3927b705,0x3bfc375e,0x2bd9bb1a,0xbbedb475,0x304e3baf,0xb9ba3593,0x39963b80,0x3887b832,0xba99bad0,
0xad7e3ad0,0x3bf83832,0xb7b7bbff,0xbb0228b6,0xb9febb6e,0xb94d35f1,0x3bed3887,0x304eba99,0x3bd43414,0xb2a1bbbc,0xb9963534,0x39ba3b91,0xb6aa3900,0x3b463a3f,0xb115bba0,0xbbe6b4d5,
0xa2483ae9,0x3c003807,0xba99bb30,0xb8873705,0xbad0bb02,0xb83237b7,0x3b462d7e,0xb6aabbf8,0x3b1a28b6,0xb75ebbff,0xaf0e3a7c,0x3bf438b0,0xabd93ab5,0x3bfc385d,0xba5ebb5a,0xb8d8364e,
0x2bd93b02,0x3bfc37b7,0xbbedb927,0xb04e3a1f,0xbb6eba7c,0xb5f138b0,0x385db6aa,0xbab5bb46,0x39dcb1db,0xb972bbdd,0x38323c00,0x3ad02248,0x34d53bbc,0x3ba03414,0xbbf4b705,0x2f0e3b30,
0x304e3b1a,0x3bed375e,0xbb91b475,0x35343baf,0xbbd4b9dc,0xb2a13972,0x2248ba7c,0xbc00b8b0,0x3832b64e,0xbad0bb5a,0x3b803a99,0x3593b887,0x39003bfc,0x3a3fabd9,0xb9273414,0x3a1f3bbc,
0x32a13b30,0x3bd43705,0xb996304e,0x39ba3bed,0xbbffb927,0xa8b63a1f,0xb832bbf4,0xbad0af0e,0x3475b8b0,0xbbafba7c,0x3ba03593,0xb4d5bb80,0x3ae93b6e,0x3807b5f1,0x2bd93a99,0x3bfc3887,
0x34753b46,0x3baf36aa,0xb4d53832,0x3ba03ad0,0xbbedb85d,0x304e3ab5,0xbb30bb5a,0xb705364e,0x2248b9fe,0xbc00b94d,0x3887b414,0xba99bbbc,0x3be63a1f,0x3115b927,0x39dc3bf4,0x3972af0e,
0x35933b5a,0x3b80364e,0x31153a99,0x3be63887,0xbba0b705,0x34d53b30,0xbbf4b8d8,0x2f0e3a5e,0xb414bb02,0xbbbcb7b7,0xabd9ba1f,0xbbfcb927,0x3bd43832,0xb2a1bad0,0x3c003972,0xa248b9dc,
0x36aa3b6e,0x3b4635f1,0x38b03bdd,0x3a7c31db,0xbb1ab534,0x375e3b91,0xba3fb04e,0x39003bed,0xb807bbaf,0xbae9b475,0xb94dbbf8,0xb9fead7e,0x3ab53365,0xb85dbbc9,0x39ba28b6,0xb996bbff,
0x37b73b80,0x3b023593,0x3b1a3bc9,0x375eb365,0xba5eb2a1,0x38d83bd4,0xb53435f1,0x3b913b6e,0xb9babbfc,0xb996abd9,0xbbddbae9,0xb1db3807,0x38b0ad7e,0xba7cbbf8,0x28b6b900,0xbbffba3f,
0x385d3b91,0x3ab53534,0x3c003a5e,0x2248b8d8,0xb972ad7e,0x39dc3bf8,0x33653a3f,0x3bc93900,0xbb02bbe6,0xb7b73115,0xbb1ab6aa,0x375e3b46,0x3414b64e,0xbbbcbb5a,0xb94dbbdd,0xb9feb1db,
0x38d83ba0,0x3a5e34d5,0x3b3037b7,0xb705bb02,0xb85d28b6,0x3ab53bff,0x39ba3be6,0x39963115,0xbbc9bb6e,0xb36535f1,0xb6aa31db,0x3b463bdd,0xaf0eb94d,0xbbf4b9fe,0xbbf8bae9,0xad7e3807,
0x394d3baf,0x39fe3475,0x38d82d7e,0xba5ebbf8,0xb64e3115,0x3b5a3be6,0x3bd43b80,0x32a1b593,0xbbffba99,0x28b63887,0x336539ba,0x3bc93996,0xb75ebae9,0xbb1ab807,0xba3fb534,0x39003b91,
0x39ba3bbc,0x39963414,0x31dbb534,0xbbddbb91,0xb3653475,0x3bc93baf,0x3b803927,0xb593ba1f,0xbba0b972,0x34d539dc,0x3a3f3be6,0x39003115,0xb9febbd4,0xb94db2a1,0xb04e35f1,0x3bed3b6e,
0x3a1f3bc9,0x39273365,0xb475b972,0xbbafb9dc,0xabd9364e,0x3bfc3b5a,0x38d831db,0xba5ebbdd,0xbab5b807,0x385d3ae9,0x3c003b30,0x2248b705,0xbb80bbf4,0xb5932f0e,0x38b03b1a,0x3a7c375e,
0x3a7c3bd4,0x38b032a1,0xb972bb5a,0xb9dcb64e,0x2f0e3807,0x3bf43ae9,0x2d7eb534,0xbbf8bb91,0xb94db4d5,0x39fe3ba0,0x3a5e37b7,0xb8d8bb02,0xbc00bb46,0x224836aa,0x3bdd3bc9,0x31dbb365,
0x3ad03bdd,0x383231db,0xbb80bc00,0xb5932248,0x347538d8,0x3baf3a5e,0xb75eb9fe,0xbb1ab94d,0xb705ad7e,0x3b303bf8,0x3414af0e,0xbbbcbbf4,0xbb6eb9dc,0x35f13972,0x3ab538b0,0xb85dba7c,
0x3b1a3be6,0x375e3115,0xbbf4bb46,0x2f0e36aa,0x37053996,0x3b3039ba,0xbae9bbd4,0xb807b2a1,0xb1db304e,0x3bdd3bed,0xb64eb94d,0xbb5ab9fe,0xb9dcb7b7,0x39723b02,0x3365ad7e,0xbbc9bbf8,
0x3b5a3bed,0x364e304e,0xbab5b94d,0x385d39fe,0x38b03a3f,0x3a7c3900,0xbbffbba0,0x28b634d5,0x2d7e3593,0x3bf83b80,0xbb02bbc9,0xb7b7b365,0xb705b1db,0x3b303bdd,0xb807b9ba,0xbae9b996,
0x3b913bf4,0x35342f0e,0xb807b4d5,0x3ae93ba0,0x39ba3ad0,0x39963832,0xba99b972,0x388739dc,0x3593385d,0x3b803ab5,0xbbe6bb6e,0x311535f1,0xad7e304e,0x3bf83bed,0xbbafbbfc,0xb475abd9,
0x3bbc3bf8,0x34142d7e,0xabd92f0e,0x3bfc3bf4,0x3a993b46,0x388736aa,0xb64eb365,0x3b5a3bc9,0x38b039ba,0x3a7c3996,0xb972b85d,0x39dc3ab5,0x34753705,0x3baf3b30,0xbb1aba5e,0x375e38d8,
0x3bdd3bfc,0x31db2bd9,0x364e3807,0x3b5a3ae9,0x3b463ba0,0x36aa34d5,0x31153475,0x3be63baf,0x3a3f3ad0,0x39003832,0xad7e28b6,0x3bf83bff,0x38d83996,0x3a5e39ba,0xb534b2a1,0x3b913bd4,
0x3bf43bff,0x2f0e28b6,0x3a1f3a7c,0x392738b0,0x3bbc3bdd,0x341431db,0x394d39ba,0x39fe3996,0x3b5a3b91,0x364e3534,0x385d38d8,0x3ab53a5e,0x3ad03b1a,0x3832375e,0x36aa37b7,0x3b463b02,
0x3bff3c00,0x28b62248,0x3bc93bd4,0x336532a1,0x3bf83bfc,0x2d7e2bd9,0x3baf3bbc,0x34753414,0x3bed3bf4,0x304e2f0e,0x3b913ba0,0x353434d5,0x3bdd3be6,0x31db3115,0x3b6e3b80,0x35f13593,
0xb5933b6e,0x3b8035f1,0xb1153bdd,0x3be631db,0x34d5bb91,0xbba0b534,0x2f0ebbed,0xbbf4b04e,0xb4143baf,0x3bbc3475,0xabd93bf8,0x3bfc2d7e,0x32a1bbc9,0xbbd4b365,0x2248bbff,0xbc00a8b6,
0x37b73b46,0x3b02b6aa,0x3b1a3832,0x375ebad0,0xb8d8bab5,0xba5e385d,0xbb91b64e,0xb5343b5a,0x39ba39fe,0x3996b94d,0x3bdd3414,0x31dbbbbc,0xba7cb927,0xb8b03a1f,0xbbffaf0e,0xa8b63bf4,
0x3bd43534,0x32a1bb91,0x39bab8d8,0xb996ba5e,0xbbffad7e,0x28b63bf8,0xb8323a3f,0x3ad03900,0x3bafb115,0xb475bbe6,0x34d5bb46,0xbba0b6aa,0xbae9364e,0x38073b5a,0xabd93bdd,0x3bfc31db,
0x3a5eb75e,0xb8d8bb1a,0xb705bbaf,0xbb303475,0xb85d39dc,0x3ab53972,0x39ba3a7c,0x3996b8b0,0x3365bb5a,0xbbc9b64e,0xbb46b887,0xb6aa3a99,0x2f0e3bfc,0x3bf42bd9,0x3bf83414,0x2d7ebbbc,
0x2bd9bbaf,0xbbfcb475,0xbbedad7e,0x304e3bf8,0x35f13be6,0x3b6eb115,0x3ab5b593,0xb85dbb80,0xb9dcba99,0xb9723887,0xb83239ba,0x3ad03996,0x3ba03807,0x34d5bae9,0x2f0ebb91,0xbbf4b534,
0xb9babae9,0xb9963807,0xb1db3b30,0x3bdd3705,0x3bc937b7,0x3365bb02,0xb593bbf8,0xbb802d7e,0xbba028b6,0x34d53bff,0x3a3f3a7c,0x3900b8b0,0x394db85d,0xb9febab5,0xbbedb64e,0xb04e3b5a,
0xbbf8b365,0x2d7e3bc9,0x3b0239dc,0x37b7b972,0x39feb64e,0xb94dbb5a,0xbbedb1db,0x304e3bdd,0xb2a13ae9,0x3bd43807,0x39bab705,0xb996bb30,0xb6aabbf4,0xbb462f0e,0xb1153b1a,0x3be6375e,
0xb8b0385d,0x3a7c3ab5,0x39dcb5f1,0xb972bb6e,0xaf0ebbbc,0xbbf4b414,0xad7e3b30,0x3bf83705,0x39fe3b1a,0x394db75e,0xb8d8bbaf,0xba5e3475,0xbc00b593,0x22483b80,0x3bdd3832,0x31dbbad0,
0x33653bdd,0x3bc931db,0xb6aabc00,0xbb462248,0xbb02ba5e,0xb7b738d8,0x3ba0394d,0x34d5b9fe,0x3b912d7e,0xb534bbf8,0xbae92f0e,0x38073bf4,0xb64e3972,0x3b5a39dc,0x32a1ba7c,0xbbd4b8b0,
0x3b1a3a7c,0x375eb8b0,0xbbf4b593,0x2f0e3b80,0xbb30a248,0x37053c00,0x3807b85d,0xbae9bab5,0x31dbba5e,0xbbddb8d8,0x364e3bfc,0x3b5a2bd9,0x39723baf,0x39dcb475,0xbbc9b927,0xb3653a1f,
0x3b6e304e,0xb5f1bbed,0xb2a139fe,0x3bd4394d,0xb1153a3f,0x3be63900,0xb9dcbba0,0xb97234d5,0xba1fbb80,0xb9273593,0x3baf3365,0xb475bbc9,0x3b9131db,0xb534bbdd,0xb41439ba,0x3bbc3996,
0x3534b900,0xbb91ba3f,0x3ae93b1a,0x3807b75e,0x39ba3bc9,0x3996b365,0xba9928b6,0x38873bff,0xbb80b2a1,0x35933bd4,0xb115bb5a,0xbbe6b64e,0x2d7eba5e,0xbbf8b8d8,0x3baf39fe,0x3475b94d,
0xb807bbf8,0xbae9ad7e,0x39feaf0e,0xb94dbbf4,0x3bdd36aa,0xb1dbbb46,0x35f13bc9,0x3b6e3365,0xb11539ba,0x3be63996,0xbbffb85d,0x28b63ab5,0xbb02bb30,0xb7b73705,0x34d5b8d8,0xbba0ba5e,
0xbbddb9fe,0xb1db394d,0xb64ebbbc,0xbb5ab414,0x36aab75e,0xbb46bb1a,0x3be637b7,0xb115bb02,0x3a3f3bc9,0x3900b365,0xad7e39dc,0x3bf83972,0xba5ea248,0x38d83c00,0xbb91bab5,0xb534385d,
0xba3fa8b6,0x39003bff,0xbbf8b8b0,0x2d7e3a7c,0xb807bbdd,0xbae9b1db,0x2bd9b9ba,0xbbfcb996,0x3b6e3534,0xb5f1bb91,0x3bd43a5e,0x32a1b8d8,0x33653b1a,0x3bc9375e,0xb59337b7,0x3b803b02,
0xa8b63996,0x3bff39ba,0xb365385d,0x3bc93ab5,0xbbf8b9fe,0xad7e394d,0xbbafbae9,0xb4753807,0x304eb900,0xbbedba3f,0x3534b75e,0xbb91bb1a,0x3bdd3a7c,0x31dbb8b0,0x3b6e3b46,0x35f1b6aa,
0x39dc3c00,0x3972a248,0x3ad03bd4,0x3832b2a1,0xb9272bd9,0x3a1f3bfc,0xb7b73414,0x3b023bbc,0xba5ebbf4,0xb8d82f0e,0xbb30bba0,0xb70534d5,0x3887b115,0xba99bbe6,0x364eb593,0xbb5abb80,
0x3bf43972,0xaf0eb9dc,0x3a1f3115,0xb927bbe6,0x34143a99,0x3bbc3887,0x39fe3c00,0x394d2248,0xbb5ab705,0x364e3b30,0xb85d304e,0x3ab53bed,0xb832bba0,0xbad0b4d5,0xbb46bbaf,0xb6aa3475,
0x3887abd9,0xba99bbfc,0xb5f1bae9,0xbb6eb807,0x3b803ba0,0x3593b4d5,0x3a7c3475,0xb8b0bbaf,0xaf0e3832,0x3bf43ad0,0x3a1f3bff,0x392728b6,0xbbedb996,0x304e39ba,0xb70532a1,0x3b303bd4,
0xb414ba1f,0xbbbcb927,0xbbfcba3f,0x2bd93900,0x3a993593,0xb887bb80,0xb64ebad0,0xbb5ab832,0x3a7c3c00,0x38b02248,0x39dc32a1,0xb972bbd4,0xb4753534,0x3baf3b91,0x3b1a3bed,0x375eb04e,
0xbb30bbf4,0xb7052f0e,0xb41434d5,0x3bbc3ba0,0x2248b832,0xbc00bad0,0xbbddb9dc,0x31db3972,0x3b46385d,0xb6aabab5,0xb8b0bb6e,0xba7cb5f1,0x3a1f3bed,0x3927304e,0x37b7abd9,0xbb02bbfc,
0xbb5ab8d8,0x364e3a5e,0x3ab53bfc,0x385d2bd9,0xba7cbbf4,0xb8b0af0e,0xa8b6375e,0x3bff3b1a,0x2d7eb6aa,0xbbf8bb46,0xbb02b832,0x37b73ad0,0x3b303887,0xb705ba99,0xbae9bc00,0xb807a248,
0xb4d53115,0x3ba03be6,0x3a3f36aa,0xb900bb46,0xbb91b996,0x353439ba,0x3bbc3bd4,0x3414b2a1,0xba99bbed,0xb887b04e,0x35f139fe,0x3b6e394d,0xa8b6b7b7,0xbbffbb02,0xb832ad7e,0x3ad03bf8,
0x38323a99,0x3ad03887,0xb593b996,0xbb80b9ba,0xb475304e,0x3baf3bed,0x375e2bd9,0xbb1abbfc,0xbb30b927,0x37053a1f,0x3bbc3a3f,0xb414b900,0xbb6ebbff,0xb5f128b6,0x3ab53be6,0x385d3115,
0x3be63bd4,0x3115b2a1,0xbbffbb5a,0x28b6364e,0x39003ae9,0x3a3f3807,0xba1fbb91,0xb927b534,0xabd934d5,0x3bfc3ba0,0xb04eb7b7,0xbbedbb02,0xb9bab6aa,0x39963b46,0x38873365,0xba99bbc9,
0x3a1f3832,0xb927bad0,0xb47528b6,0x3baf3bff,0x3bfc3b6e,0xabd9b5f1,0xba5eb887,0x38d83a99,0x3ab53bbc,0x385d3414,0xbc00bb91,0x22483534,0x35933900,0x3b803a3f,0xba7cbba0,0xb8b0b4d5,
0x2248b414,0xbc00bbbc,0x3a993b91,0x38873534,0x38323475,0xbad0bbaf,0x36aa3927,0x3b463a1f,0x3b1a39dc,0xb75eb972,0xaf0e3115,0x3bf43be6,0x3bfc3bd4,0x2bd9b2a1,0xb8d8b5f1,0x3a5e3b6e,
0xb9febb02,0xb94db7b7,0x3a5e3927,0xb8d8ba1f,0xb64eb8b0,0xbb5aba7c,0x3bd43b46,0xb2a1b6aa,0x28b6b1db,0xbbffbbdd,0x3bc93c00,0x33652248,0x375e3414,0xbb1abbbc,0x3a3f3b30,0x39003705,
0xbbedbba0,0x304e34d5,0xb534b7b7,0xbb91bb02,0xbbd4bbff,0xb2a1a8b6,0x2248b115,0xbc00bbe6,0xbad0bb6e,0xb832b5f1,0x359331db,0xbb80bbdd,0xb900b9fe,0xba3fb94d,0x39273807,0xba1fbae9,
0xb85db705,0x3ab53b30,0xbc00bbed,0x2248304e,0xb9dcb927,0x39723a1f,0xbbc9bbf4,0xb365af0e,0xbb02ba7c,0x37b738b0,0xbb1abb80,0xb75eb593,0xbbbcbb6e,0x341435f1,0xb9feba99,0xb94db887,
0x34753593,0x3baf3b80,0xb4d5b365,0x3ba03bc9,0x304e32a1,0x3bed3bd4,0xb705b5f1,0x3b303b6e,0xa2482bd9,0x3c003bfc,0xb887b807,0x3a993ae9,0xb115ad7e,0x3be63bf8,0xb972b900,0x39dc3a3f,
0x3b463b5a,0x36aa364e,0x3a7c3a99,0x38b03887,0x3b1a3b30,0x375e3705,0x3a3f3a5e,0x390038d8,0x3ae93b02,0x380737b7,0x39fe3a1f,0x394d3927,0x3ab53ad0,0x385d3832,0x39ba39dc,0x39963972,
0x28b63c00,0x3bffa248,0x33653bd4,0x3bc9b2a1,0xad7ebbfc,0xbbf82bd9,0xb475bbbc,0xbbaf3414,0x304e3bf4,0x3bedaf0e,0x35343ba0,0x3b91b4d5,0xb1dbbbe6,0xbbdd3115,0xb5f1bb80,0xbb6e3593,
0x3bf4a8b6,0xaf0ebbff,0x3a1fb8b0,0xb927ba7c,0xbbbc31db,0x34143bdd,0xb94d3996,0x39fe39ba,0x3b5ab534,0xb64ebb91,0x385dba5e,0xbab5b8d8,0xbad0375e,0x38323b1a,0xb6aa3b02,0x3b4637b7,
0xb1dbbbfc,0xbbdd2bd9,0xbb5ab807,0xb64e3ae9,0x36aa3ba0,0x3b46b4d5,0x3be63475,0x3115bbaf,0xb900bad0,0xba3f3832,0xbbf8a8b6,0x2d7e3bff,0x3a5e3996,0x38d8b9ba,0x3b91b2a1,0xb534bbd4,
0xbbbc2d7e,0x34143bf8,0x2bd93bf4,0x3bfc2f0e,0x3a99b6aa,0xb887bb46,0xb64ebbc9,0xbb5a3365,0xb8b03996,0x3a7c39ba,0x39723ab5,0x39dcb85d,0x3475bb30,0xbbafb705,0xbb1ab8d8,0xb75e3a5e,
0x35343bf4,0x3b91af0e,0x3ae9b4d5,0xb807bba0,0xb996bad0,0xb9ba3832,0xb8873972,0x3a9939dc,0x3b80385d,0x3593bab5,0x3115bb6e,0xbbe6b5f1,0xbbf8b04e,0x2d7e3bed,0x34753bfc,0x3bafabd9,
0x3b5ab04e,0xb64ebbed,0xbab5b9fe,0xb85d394d,0xb8b03900,0x3a7c3a3f,0x3bff34d5,0x28b6bba0,0x2d7ebb80,0xbbf8b593,0xbb023365,0x37b73bc9,0x37053bdd,0x3b30b1db,0x3807b996,0xbae9b9ba,
0xb75ebbe6,0xbb1a3115,0xaf0e3b46,0x3bf436aa,0x3b303996,0x3705b9ba,0xb807bbd4,0xbae932a1,0xbbddb04e,0x31db3bed,0x3b5a394d,0x364eb9fe,0x3972b7b7,0xb9dcbb02,0xbbc9ad7e,0x33653bf8,
0xbad031db,0x38323bdd,0x3b802248,0xb593bc00,0x3475ba5e,0xbbafb8d8,0xb75e394d,0x3b1a39fe,0x37053bf8,0x3b30ad7e,0xb414bbf4,0xbbbcaf0e,0xbb6eb972,0xb5f139dc,0x3ab53a7c,0x385db8b0,
0x38b03bd4,0x3a7cb2a1,0xb9dcbb5a,0xb972364e,0xbbf4b807,0xaf0e3ae9,0x3bf83534,0xad7ebb91,0x39feb4d5,0xb94dbba0,0xb8d837b7,0x3a5e3b02,0xa2483b46,0x3c0036aa,0xb1dbbbc9,0xbbddb365,
0x3a1fb365,0xb927bbc9,0xb47539dc,0x3baf3972,0x2bd93b5a,0x3bfc364e,0xb8d8bbdd,0xba5e31db,0xbab5bae9,0xb85d3807,0x3c003705,0xa248bb30,0x3b802f0e,0xb593bbf4,0xb8b0375e,0x3a7c3b1a,
0xb996bbbc,0xb9ba3414,0x3bdd3534,0xb1dbbb91,0x3bc93475,0xb365bbaf,0xb5933927,0x3b803a1f,0xb4d53972,0x3ba039dc,0xb900bbe6,0xba3f3115,0xb94dbbd4,0xb9fe32a1,0x3bed35f1,0xb04ebb6e,
0xb94d3475,0x39fe3baf,0xb8d8bbf8,0xba5e2d7e,0xb64ebbe6,0xbb5ab115,0x3bd43593,0xb2a1bb80,0x3bff3887,0x28b6ba99,0xb3653996,0x3bc939ba,0xb75e3807,0x3b1a3ae9,0xba3fbb91,0xb9003534,
0x3a5e3ba0,0x38d8b4d5,0xb70537b7,0x3b303b02,0xbab5a8b6,0x385d3bff,0xb996bbe6,0xb9ba3115,0xb365bb6e,0xbbc9b5f1,0x3b4631db,0xb6aabbdd,0x3bf4394d,0x2f0eb9fe,0x2d7e3ae9,0x3bf83807,
0x385db534,0xbab5bb91,0x3c0038d8,0xa248ba5e,0x39723bf8,0x39dcad7e,0xb3653900,0x3bc93a3f,0xbb02b115,0x37b73be6,0xbb1abb46,0xb75e36aa,0xb414bb5a,0xbbbcb64e,0x394db1db,0xb9febbdd,
0xbb02bb80,0xb7b73593,0xb75ebbc9,0xbb1ab365,0x38d8b2a1,0xba5ebbd4,0x3b9135f1,0xb534bb6e,0x39963bfc,0x39baabd9,0x31db3ae9,0x3bdd3807,0xba7cad7e,0x38b03bf8,0xbbffb900,0x28b63a3f,
0xb6aa35f1,0x3b463b6e,0xb8b031db,0x3a7c3bdd,0xbb1abb91,0xb75e3534,0xba3fbbed,0xb900304e,0x3807b475,0xbae9bbaf,0x394dad7e,0xb9febbf8,0x3ab53bc9,0x385db365,0x39ba3bff,0x3996a8b6,
0x3b803b5a,0x3593b64e,0x3be63a99,0x3115b887,0xb4d53705,0x3ba03b30,0xaf0e38d8,0x3bf43a5e,0xbbbcbb02,0xb41437b7,0xbbfcba1f,0xabd93927,0x32a1b832,0xbbd4bad0,0x2248b972,0xbc00b9dc,
0x3475b6aa,0xbbafbb46,0xb4d5bad0,0xbba0b832,0x3bed3ab5,0x304eb85d,0x3b30364e,0xb705bb5a,0x2248394d,0x3c0039fe,0x38873bbc,0x3a993414,0xbbe6b927,0x31153a1f,0xb9dcaf0e,0x39723bf4,
0xbbd4bb30,0xb2a13705,0xb9bab04e,0x39963bed,0xa8b6b927,0xbbffba1f,0xbad0bbf4,0xb8322f0e,0x3baf38b0,0xb475ba7c,0x34d5b593,0xbba0bb80,0x38073b6e,0x3ae935f1,0x3bfc3a99,0x2bd9b887,
0xb04e375e,0x3bed3b1a,0x3b913baf,0x3534b475,0xbbd4b972,0x32a139dc,0x224838b0,0x3c003a7c,0xb832bb5a,0xbad0b64e,0xbb80b887,0x35933a99,0x39002bd9,0xba3fbbfc,0xb927bbbc,0xba1fb414,
0x3bfc3b02,0x2bd9b7b7,0xb04eb927,0xbbedba1f,0x35f13a7c,0x3b6e38b0,0x3ab536aa,0xb85dbb46,0xb972b1db,0x39dc3bdd,0x3ad03c00,0x3832a248,0xbba0bbbc,0xb4d53414,0xaf0e3705,0x3bf43b30,
0xa248b807,0xbc00bae9,0xba99b705,0x38873b30,0x3ad037b7,0xb832bb02,0xbb46bbf8,0xb6aa2d7e,0x3b1a3bff,0x375ea8b6,0xaf0eb8b0,0xbbf4ba7c,0x2bd9385d,0x3bfc3ab5,0x3a5e364e,0xb8d8bb5a,
0xbbf8bad0,0x2d7e3832,0x3b023bff,0x37b728b6,0xb94dbb6e,0xb9feb5f1,0x304e3887,0x3bed3a99,0x32a1b414,0xbbd4bbbc,0xb9bab534,0x39963b91,0x3b463900,0xb6aaba3f,0xbbe6bba0,0xb11534d5,
0x3115385d,0x3be63ab5,0x28b6b5f1,0xbbffbb6e,0xb900b414,0x3a3f3bbc,0x3a1f3705,0xb927bb30,0xbbfcbb1a,0x2bd9375e,0x3bed3baf,0x304eb475,0xb9babb80,0xb996b593,0x38873ad0,0x3a993832,
0x3bc93a99,0xb365b887,0xbb46b996,0x36aa39ba,0x3b023bed,0x37b7304e,0xbba0bbfc,0xb4d52bd9,0x35343927,0x3b913a1f,0xb807ba3f,0xbae9b900,0xb64ea8b6,0x3b5a3bff,0x32a1b115,0xbbd4bbe6,
0xb4d5b8b0,0xbba0ba7c,0x3a3f3b80,0x39003593,0x35342248,0xbb91bc00,0x3414385d,0x3bbc3ab5,0x3a9938d8,0xb887ba5e,0xb5f1abd9,0x3b6e3bfc,0x3bff3baf,0x28b6b475,0xbad0b927,0x38323a1f,
0xbb6eba5e,0x35f138d8,0x32a1abd9,0xbbd4bbfc,0xbbe6bbf4,0xb1152f0e,0x3972375e,0xb9dcbb1a,0xba1fbb46,0xb927b6aa,0x3baf3ad0,0xb475b832,0xb534b887,0xbb91ba99,0x3bbc3c00,0x3414a248,
0x37053900,0x3b303a3f,0xbbbcbb1a,0x3414375e,0x22483365,0x3c003bc9,0xbbddbbff,0xb1db28b6,0xb6aab2a1,0x3b463bd4,0xba7cbb5a,0xb8b0b64e,0xba1fb8d8,0x39273a5e,0xb7b7b94d,0xbb02b9fe,
0x3ae93a1f,0xb807b927,0x394d3a3f,0x39fe3900,0x3bdd3b80,0xb1dbb593,0x35f13832,0x3b6e3ad0,0x3be63c00,0x3115a248,0x28b632a1,0x3bff3bd4,0x3b023b91,0x37b73534,0xb4d5b04e,0x3ba03bed,
0xb887b94d,0xba99b9fe,0x35f13414,0xbb6ebbbc,0xb593b75e,0xbb80bb1a,0x38b037b7,0xba7cbb02,0xaf0eb365,0xbbf4bbc9,0x3a1f3972,0xb927b9dc,0x304e2248,0xbbedbc00,0x3b303ab5,0xb705b85d,
0xba3fb9dc,0x39003972,0xbbf8bbe6,0x2d7e3115,0xbae9ba99,0x38073887,0xbbfcbc00,0xabd92248,0xbb6ebb30,0x35f13705,0xbbd4bbed,0xb2a1b04e,0xbbc9bba0,0x336534d5,0xbb80bbaf,0xb593b475,
0x39723996,0x39dc39ba,0x3832385d,0x3ad03ab5,0x3927394d,0x3a1f39fe,0x37b73807,0x3b023ae9,0x38d83900,0x3a5e3a3f,0x3705375e,0x3b303b1a,0x388738b0,0x3a993a7c,0x364e36aa,0x3b5a3b46,
0x36aa3b5a,0x3b46b64e,0x38b03a99,0x3a7cb887,0xb75ebb30,0xbb1a3705,0xb900ba5e,0xba3f38d8,0x38073b02,0x3ae9b7b7,0x394d3a1f,0x39feb927,0xb85dbad0,0xbab53832,0xb996b9dc,0xb9ba3972,
0x3475bb80,0xbbafb593,0xb4d5bbc9,0xbba03365,0xb04e3bd4,0x3bed32a1,0x37053b6e,0x3b30b5f1,0xa248bbfc,0xbc00abd9,0xb887bae9,0xba993807,0x31153bf8,0x3be6ad7e,0x39723a3f,0x39dcb900,
0xbab53705,0x385d3b30,0xa2483bed,0x3c00304e,0x3972b927,0xb9dcba1f,0xb365bbf4,0xbbc92f0e,0xb7b73a7c,0x3b0238b0,0x375e3b80,0x3b1ab593,0x3414bb6e,0xbbbcb5f1,0xb94dba99,0xb9fe3887,
0x3bed34d5,0x304ebba0,0x3534bb02,0xbb91b7b7,0xbbd428b6,0x32a13bff,0x22483be6,0x3c003115,0x3ad0b5f1,0xb832bb6e,0xb593bbdd,0xbb8031db,0xb900394d,0x3a3f39fe,0x39273ae9,0x3a1fb807,
0xb94dbb02,0xb9fe37b7,0xb8d83927,0x3a5e3a1f,0x3b5a38b0,0x364eba7c,0x32a1bb46,0xbbd4b6aa,0xbbffb1db,0x28b63bdd,0x33653c00,0x3bc9a248,0x3b1ab414,0xb75ebbbc,0xb900bb30,0xba3f3705,
0x22483bbc,0x3c003414,0x3a99b534,0xb887bb91,0xb832bbaf,0xbad03475,0xb6aa3a1f,0x3b463927,0x3b1a3972,0x375eb9dc,0xaf0ebbe6,0xbbf4b115,0xbbfcb2a1,0x2bd93bd4,0x38d83b6e,0x3a5eb5f1,
0x3927b832,0xba1fbad0,0xbbafa8b6,0x34753bff,0xabd93b6e,0x3bfc35f1,0x38d8b887,0xba5eba99,0xb85dbbbc,0xbab53414,0xa2483b91,0x3c003534,0x3b803900,0x3593ba3f,0xb8b0bba0,0xba7c34d5,
0xbbe6b2a1,0x31153bd4,0x3bff364e,0x28b6bb5a,0x3900b807,0xba3fbae9,0xba1f3534,0x39273b91,0x2bd93ba0,0x3bfc34d5,0x304ebb02,0xbbedb7b7,0xb9babb46,0xb99636aa,0x38873bc9,0x3a99b365,
0x3ad03a99,0x3832b887,0xbb80b996,0xb59339ba,0xbbafb04e,0x34753bed,0x3b1aabd9,0xb75ebbfc,0x3705b927,0xbb30ba1f,0xb4143a3f,0x3bbc3900,0x35f13bff,0x3b6e28b6,0xb85dbbe6,0xbab53115,
0xb4d5bbe6,0xbba0b115,0x3a3f3b46,0x3900b6aa,0x3b9139ba,0x3534b996,0xbbbcb2a1,0x34143bd4,0xba99304e,0x38873bed,0x35f1b94d,0xbb6eb9fe,0x28b6bb02,0xbbffb7b7,0x38323bf8,0x3ad0ad7e,
0xb64e38d8,0x3b5a3a5e,0xb85dbbfc,0xbab52bd9,0xb8b0bbf4,0xba7c2f0e,0x3bff375e,0xa8b6bb1a,0x3bf836aa,0xad7ebb46,0xb7b73832,0x3b023ad0,0xb7053887,0x3b303a99,0xb807bc00,0xbae92248,
0x3b302f0e,0xb705bbf4,0x34143ba0,0x3bbc34d5,0x22483ad0,0x3c003832,0xbbddb972,0xb1db39dc,0xbb46bab5,0xb6aa385d,0x38b0b5f1,0xba7cbb6e,0x3a1fb04e,0xb927bbed,0x37b73bfc,0x3b022bd9,
0xbbbcba1f,0xb4143927,0x2bd9ba3f,0xbbfcb900,0x3887b593,0xba99bb80,0x3b5a3ad0,0x364eb832,0x38b03c00,0x3a7ca248,0xb97232a1,0x39dc3bd4,0xbbafb534,0x34753b91,0xb75ebbed,0xbb1ab04e,
0x38873bfc,0x3a992bd9,0xb5f13807,0x3b6e3ae9,0xbb80b4d5,0x35933ba0,0xba7cbbaf,0xb8b03475,0xaf0ebad0,0xbbf4b832,0x3a1fa8b6,0xb927bbff,0x3bed39ba,0x304eb996,0x37053bd4,0x3b3032a1,
0x2f0eb972,0xbbf4b9dc,0x3927b115,0xba1fbbe6,0x3bbc3a99,0x3414b887,0x394d3c00,0x39fea248,0xb64e3705,0x3b5a3b30,0xbab5b04e,0x385d3bed,0xbad0bba0,0xb83234d5,0xb6aabbaf,0xbb46b475,
0xb9dca248,0x39723c00,0xbad0b2a1,0x38323bd4,0xb927bbfc,0xba1fabd9,0xb7b7bbbc,0xbb02b414,0x3a5e2f0e,0xb8d8bbf4,0x3b3034d5,0xb705bba0,0x38873be6,0x3a993115,0x364e3b80,0x3b5a3593,
0x3bff3996,0xa8b6b9ba,0x3bc9385d,0xb365bab5,0x2d7e39fe,0x3bf8394d,0x34753ae9,0x3baf3807,0xbbedb900,0x304e3a3f,0xbb91b75e,0x35343b1a,0xb1dbba7c,0xbbddb8b0,0xb5f1bb46,0xbb6eb6aa,
0xba3fbbff,0xb90028b6,0xbbf8ba7c,0xad7e38b0,0x3807b1db,0xbae9bbdd,0xabd9b996,0xbbfcb9ba,0x3b6e3b91,0x35f1b534,0x3bd438d8,0xb2a1ba5e,0xb365375e,0x3bc93b1a,0x35933b02,0x3b8037b7,
0x31db39fe,0x3bdd394d,0x3b5a3bbc,0x364eb414,0xbb46b75e,0x36aa3b1a,0xb11537b7,0x3be63b02,0xb900bbc9,0xba3fb365,0xbbf8b9dc,0x2d7e3972,0x38d8a248,0xba5ebc00,0xb534bab5,0xbb91b85d,
0x3807ad7e,0xbae9bbf8,0xb9febbf4,0xb94daf0e,0x3bdd3b46,0x31dbb6aa,0x35f1b365,0xbb6ebbc9,0x31153996,0x3be639ba,0x3bff3ab5,0x28b6b85d,0xbb02b705,0x37b73b30,0x34d53a5e,0x3ba038d8,
0xbb91b900,0x35343a3f,0x38073b1a,0x3ae9375e,0xb996bbc9,0xb9bab365,0xb887a8b6,0x3a993bff,0x3593b2a1,0xbb80bbd4,0xbbe6bb5a,0xb115364e,0x3bf83a5e,0xad7eb8d8,0xb475b9fe,0xbbafb94d,
0x3b6e3bed,0x35f1b04e,0xb2a1b94d,0xbbd4b9fe,0x31153900,0x3be63a3f,0x39dc34d5,0xb972bba0,0xba1fb593,0x39273b80,0x3baf3bc9,0x3475b365,0xbb91bbdd,0xb53431db,0x34143996,0x3bbc39ba,
0xb75eba7c,0xbb1ab8b0,0xaf0e3593,0x3bf43b80,0x3705a248,0xbb30bc00,0xbae9b85d,0x38073ab5,0x3bdd3a5e,0xb1dbb8d8,0xbb5abbfc,0xb64e2bd9,0x39dc3baf,0x39723475,0xb365b927,0xbbc9ba1f,
0xb36531db,0x3bc93bdd,0x36aa2248,0xbb46bc00,0xbb02b8d8,0x37b73a5e,0x3ba039fe,0xb4d5b94d,0xbb91bbf8,0xb5342d7e,0x3ae93bf4,0x38072f0e,0xb64eb9dc,0xbb5ab972,0x32a138b0,0x3bd43a7c,
0x3a7c385d,0xb8b0bab5,0xb972b5f1,0x39dc3b6e,0x3bf43bbc,0x2f0eb414,0xbbf8bb30,0x2d7e3705,0x394d3b1a,0x39fe375e,0xba5ebbaf,0xb8d8b475,0xa2483593,0x3c003b80,0xb1dbb832,0xbbddbad0,
0xbbf8bbc9,0xad7e3365,0x3b023972,0xb7b7b9dc,0xb9febb5a,0xb94db64e,0x3bed3bdd,0x304eb1db,0xb2a1b807,0xbbd4bae9,0x39ba3b30,0x39963705,0x36aa2f0e,0xbb46bbf4,0x3115375e,0x3be63b1a,
0x39963ae9,0x39ba3807,0xbbddbb30,0x31db3705,0x336537b7,0x3bc93b02,0xbb80bbf8,0xb593ad7e,0xb4d5a8b6,0x3ba03bff,0xb900ba7c,0xba3fb8b0,0xb9feb85d,0x394d3ab5,0xb04eb64e,0xbbedbb5a,
0xabd9b475,0xbbfcbbaf,0x3bed3bf8,0x304ead7e,0x35f13115,0xbb6ebbe6,0x3ab53b80,0x385d3593,0x39dc3887,0xb972ba99,0x38323996,0x3ad039ba,0x3ba03ae9,0xb4d5b807,0x2f0e3534,0x3bf43b91,
0xb8d8b75e,0x3a5e3b1a,0xbb30bbaf,0xb705b475,0xbab5b9dc,0x385d3972,0xb996ba7c,0xb9bab8b0,0xbbc9bb5a,0x3365364e,0xb6aab887,0xbb46ba99,0xbbf4bbfc,0xaf0e2bd9,0xad7eb414,0xbbf8bbbc,
0x3bd43b91,0xb2a1b534,0x39ba3a5e,0x399638d8,0x3bff3bf8,0x28b6ad7e,0x38323900,0x3ad03a3f,0x3baf3be6,0x34753115,0x34d536aa,0x3ba03b46,0x3ae93b5a,0x3807364e,0x2bd931db,0x3bfc3bdd,
0xbb02bb46,0xb7b7b6aa,0xb75eb832,0xbb1abad0,0xba5ebab5,0xb8d8b85d,0xb534b64e,0xbb91bb5a,0xb996b9fe,0xb9bab94d,0xb1dbb414,0xbbddbbbc,0xb8b0b927,0xba7cba1f,0xa8b6af0e,0xbbffbbf4,
0x359335f1,0x3b803b6e,0x311531db,0x3be63bdd,0x34d53534,0x3ba03b91,0x2f0e304e,0x3bf43bed,0x34143475,0x3bbc3baf,0x2bd92d7e,0x3bfc3bf8,0x32a13365,0x3bd43bc9,0x224828b6,0x3c003bff,
0x40000,0x60002,0xc0008,0xe000a,0x380034,0x3a0036,0x40003c,0x42003e,0x6c0068,0x6e006a,0x740070,0x760072,0xa0009c,0xa2009e,0xa800a4,0xaa00a6,
0xd400d0,0xd600d2,0xdc00d8,0xde00da,0x1080104,0x10a0106,0x110010c,0x112010e,0x13c0138,0x13e013a,0x1440140,0x1460142,0x170016c,0x172016e,0x1780174,0x17a0176,
0x1a401a0,0x1a601a2,0x1ac01a8,0x1ae01aa,0x1d801d4,0x1da01d6,0x1e001dc,0x1e201de,0x20c0208,0x20e020a,0x2140210,0x2160212,0x240023c,0x242023e,0x2480244,0x24a0246,
0x2740270,0x2760272,0x27c0278,0x27e027a,0x2a802a4,0x2aa02a6,0x2b002ac,0x2b202ae,0x2dc02d8,0x2de02da,0x2e402e0,0x2e602e2,0x310030c,0x312030e,0x3180314,0x31a0316,
0x3440340,0x3460342,0x34c0348,0x34e034a,0x3780374,0x37a0376,0x380037c,0x382037e,0x3ac03a8,0x3ae03aa,0x3b403b0,0x3b603b2,0x3e003dc,0x3e203de,0x3e803e4,0x3ea03e6,
0x4140410,0x4160412,0x41c0418,0x41e041a,0x4480444,0x44a0446,0x450044c,0x452044e,0x47c0478,0x47e047a,0x4840480,0x4860482,0x4b004ac,0x4b204ae,0x4b804b4,0x4ba04b6,
0x4e404e0,0x4e604e2,0x4ec04e8,0x4ee04ea,0x5180514,0x51a0516,0x520051c,0x522051e,0x54c0548,0x54e054a,0x5540550,0x5560552,0x580057c,0x582057e,0x5880584,0x58a0586,
0x5b405b0,0x5b605b2,0x5bc05b8,0x5be05ba,0x5e805e4,0x5ea05e6,0x5f005ec,0x5f205ee,0x61c0618,0x61e061a,0x6240620,0x6260622,0x650064c,0x652064e,0x6580654,0x65a0656,
0x140010,0x160012,0x120010,0x440012,0x480044,0x4a0046,0x460044,0x780046,0x7c0078,0x7e007a,0x7a0078,0xac007a,0xb000ac,0xb200ae,0xae00ac,0xe000ae,
0xe400e0,0xe600e2,0xe200e0,0x11400e2,0x1180114,0x11a0116,0x1160114,0x1480116,0x14c0148,0x14e014a,0x14a0148,0x17c014a,0x180017c,0x182017e,0x17e017c,0x1b0017e,
0x1b401b0,0x1b601b2,0x1b201b0,0x1e401b2,0x1e801e4,0x1ea01e6,0x1e601e4,0x21801e6,0x21c0218,0x21e021a,0x21a0218,0x24c021a,0x250024c,0x252024e,0x24e024c,0x280024e,
0x2840280,0x2860282,0x2820280,0x2b40282,0x2b802b4,0x2ba02b6,0x2b602b4,0x2e802b6,0x2ec02e8,0x2ee02ea,0x2ea02e8,0x31c02ea,0x320031c,0x322031e,0x31e031c,0x350031e,
0x3540350,0x3560352,0x3520350,0x3840352,0x3880384,0x38a0386,0x3860384,0x3b80386,0x3bc03b8,0x3be03ba,0x3ba03b8,0x3ec03ba,0x3f003ec,0x3f203ee,0x3ee03ec,0x42003ee,
0x4240420,0x4260422,0x4220420,0x4540422,0x4580454,0x45a0456,0x4560454,0x4880456,0x48c0488,0x48e048a,0x48a0488,0x4bc048a,0x4c004bc,0x4c204be,0x4be04bc,0x4f004be,
0x4f404f0,0x4f604f2,0x4f204f0,0x52404f2,0x5280524,0x52a0526,0x5260524,0x5580526,0x55c0558,0x55e055a,0x55a0558,0x58c055a,0x590058c,0x592058e,0x58e058c,0x5c0058e,
0x5c405c0,0x5c605c2,0x5c205c0,0x5f405c2,0x5f805f4,0x5fa05f6,0x5f605f4,0x62805f6,0x62c0628,0x62e062a,0x62a0628,0x65c062a,0x660065c,0x662065e,0x65e065c,0x18065e,
0x180018,0x4c001a,0x1a0018,0x4c001a,0x4c004c,0x80004e,0x4e004c,0x80004e,0x800080,0xb40082,0x820080,0xb40082,0xb400b4,0xe800b6,0xb600b4,0xe800b6,
0xe800e8,0x11c00ea,0xea00e8,0x11c00ea,0x11c011c,0x150011e,0x11e011c,0x150011e,0x1500150,0x1840152,0x1520150,0x1840152,0x1840184,0x1b80186,0x1860184,0x1b80186,
0x1b801b8,0x1ec01ba,0x1ba01b8,0x1ec01ba,0x1ec01ec,0x22001ee,0x1ee01ec,0x22001ee,0x2200220,0x2540222,0x2220220,0x2540222,0x2540254,0x2880256,0x2560254,0x2880256,
0x2880288,0x2bc028a,0x28a0288,0x2bc028a,0x2bc02bc,0x2f002be,0x2be02bc,0x2f002be,0x2f002f0,0x32402f2,0x2f202f0,0x32402f2,0x3240324,0x3580326,0x3260324,0x3580326,
0x3580358,0x38c035a,0x35a0358,0x38c035a,0x38c038c,0x3c0038e,0x38e038c,0x3c0038e,0x3c003c0,0x3f403c2,0x3c203c0,0x3f403c2,0x3f403f4,0x42803f6,0x3f603f4,0x42803f6,
0x4280428,0x45c042a,0x42a0428,0x45c042a,0x45c045c,0x490045e,0x45e045c,0x490045e,0x4900490,0x4c40492,0x4920490,0x4c40492,0x4c404c4,0x4f804c6,0x4c604c4,0x4f804c6,
0x4f804f8,0x52c04fa,0x4fa04f8,0x52c04fa,0x52c052c,0x560052e,0x52e052c,0x560052e,0x5600560,0x5940562,0x5620560,0x5940562,0x5940594,0x5c80596,0x5960594,0x5c80596,
0x5c805c8,0x5fc05ca,0x5ca05c8,0x5fc05ca,0x5fc05fc,0x63005fe,0x5fe05fc,0x63005fe,0x6300630,0x6640632,0x6320630,0x6640632,0x6640664,0x1c0666,0x6660664,0x1c0666,
0x1c001c,0x50001e,0x1e001c,0x50001e,0x500050,0x840052,0x520050,0x840052,0x840084,0xb80086,0x860084,0xb80086,0xb800b8,0xec00ba,0xba00b8,0xec00ba,
0xec00ec,0x12000ee,0xee00ec,0x12000ee,0x1200120,0x1540122,0x1220120,0x1540122,0x1540154,0x1880156,0x1560154,0x1880156,0x1880188,0x1bc018a,0x18a0188,0x1bc018a,
0x1bc01bc,0x1f001be,0x1be01bc,0x1f001be,0x1f001f0,0x22401f2,0x1f201f0,0x22401f2,0x2240224,0x2580226,0x2260224,0x2580226,0x2580258,0x28c025a,0x25a0258,0x28c025a,
0x28c028c,0x2c0028e,0x28e028c,0x2c0028e,0x2c002c0,0x2f402c2,0x2c202c0,0x2f402c2,0x2f402f4,0x32802f6,0x2f602f4,0x32802f6,0x3280328,0x35c032a,0x32a0328,0x35c032a,
0x35c035c,0x390035e,0x35e035c,0x390035e,0x3900390,0x3c40392,0x3920390,0x3c40392,0x3c403c4,0x3f803c6,0x3c603c4,0x3f803c6,0x3f803f8,0x42c03fa,0x3fa03f8,0x42c03fa,
0x42c042c,0x460042e,0x42e042c,0x460042e,0x4600460,0x4940462,0x4620460,0x4940462,0x4940494,0x4c80496,0x4960494,0x4c80496,0x4c804c8,0x4fc04ca,0x4ca04c8,0x4fc04ca,
0x4fc04fc,0x53004fe,0x4fe04fc,0x53004fe,0x5300530,0x5640532,0x5320530,0x5640532,0x5640564,0x5980566,0x5660564,0x5980566,0x5980598,0x5cc059a,0x59a0598,0x5cc059a,
0x5cc05cc,0x60005ce,0x5ce05cc,0x60005ce,0x6000600,0x6340602,0x6020600,0x6340602,0x6340634,0x6680636,0x6360634,0x6680636,0x6680668,0x20066a,0x66a0668,0x20066a,
0x5d605d6,0x60a05d6,0x5d605d6,0x60a060a,0x60a060a,0x63e063e,0x60a060a,0x63e063e,0x63e063e,0x672063e,0x63e063e,0x6720672,0x6720672,0x280028,0x6720672,0x280028,
0x5060506,0x53a0506,0x5060506,0x53a053a,0x53a053a,0x56e056e,0x53a053a,0x56e056e,0x56e056e,0x5a2056e,0x56e056e,0x5a205a2,0x5a205a2,0x5d605d6,0x5a205a2,0x5d605d6,
0x4360436,0x46a0436,0x4360436,0x46a046a,0x46a046a,0x49e049e,0x46a046a,0x49e049e,0x49e049e,0x4d2049e,0x49e049e,0x4d204d2,0x4d204d2,0x5060506,0x4d204d2,0x5060506,
0x3660366,0x39a0366,0x3660366,0x39a039a,0x39a039a,0x3ce03ce,0x39a039a,0x3ce03ce,0x3ce03ce,0x40203ce,0x3ce03ce,0x4020402,0x4020402,0x4360436,0x4020402,0x4360436,
0x2960296,0x2ca0296,0x2960296,0x2ca02ca,0x2ca02ca,0x2fe02fe,0x2ca02ca,0x2fe02fe,0x2fe02fe,0x33202fe,0x2fe02fe,0x3320332,0x3320332,0x3660366,0x3320332,0x3660366,
0x1c601c6,0x1fa01c6,0x1c601c6,0x1fa01fa,0x1fa01fa,0x22e022e,0x1fa01fa,0x22e022e,0x22e022e,0x262022e,0x22e022e,0x2620262,0x2620262,0x2960296,0x2620262,0x2960296,
0xf600f6,0x12a00f6,0xf600f6,0x12a012a,0x12a012a,0x15e015e,0x12a012a,0x15e015e,0x15e015e,0x192015e,0x15e015e,0x1920192,0x1920192,0x1c601c6,0x1920192,0x1c601c6,
0x260026,0x5a0026,0x260026,0x5a005a,0x5a005a,0x8e008e,0x5a005a,0x8e008e,0x8e008e,0xc2008e,0x8e008e,0xc200c2,0xc200c2,0xf600f6,0xc200c2,0xf600f6,
0x5d405d4,0x60805d4,0x5d405d4,0x6080608,0x6080608,0x63c063c,0x6080608,0x63c063c,0x63c063c,0x670063c,0x63c063c,0x6700670,0x6700670,0x260026,0x6700670,0x260026,
0x5040504,0x5380504,0x5040504,0x5380538,0x5380538,0x56c056c,0x5380538,0x56c056c,0x56c056c,0x5a0056c,0x56c056c,0x5a005a0,0x5a005a0,0x5d405d4,0x5a005a0,0x5d405d4,
0x4340434,0x4680434,0x4340434,0x4680468,0x4680468,0x49c049c,0x4680468,0x49c049c,0x49c049c,0x4d0049c,0x49c049c,0x4d004d0,0x4d004d0,0x5040504,0x4d004d0,0x5040504,
0x3640364,0x3980364,0x3640364,0x3980398,0x3980398,0x3cc03cc,0x3980398,0x3cc03cc,0x3cc03cc,0x40003cc,0x3cc03cc,0x4000400,0x4000400,0x4340434,0x4000400,0x4340434,
0x2940294,0x2c80294,0x2940294,0x2c802c8,0x2c802c8,0x2fc02fc,0x2c802c8,0x2fc02fc,0x2fc02fc,0x33002fc,0x2fc02fc,0x3300330,0x3300330,0x3640364,0x3300330,0x3640364,
0x1c401c4,0x1f801c4,0x1c401c4,0x1f801f8,0x1f801f8,0x22c022c,0x1f801f8,0x22c022c,0x22c022c,0x260022c,0x22c022c,0x2600260,0x2600260,0x2940294,0x2600260,0x2940294,
0xf400f4,0x12800f4,0xf400f4,0x1280128,0x1280128,0x15c015c,0x1280128,0x15c015c,0x15c015c,0x190015c,0x15c015c,0x1900190,0x1900190,0x1c401c4,0x1900190,0x1c401c4,
0x240024,0x580024,0x240024,0x580058,0x580058,0x8c008c,0x580058,0x8c008c,0x8c008c,0xc0008c,0x8c008c,0xc000c0,0xc000c0,0xf400f4,0xc000c0,0xf400f4,
0x5d205d2,0x60605d2,0x5d205d2,0x6060606,0x6060606,0x63a063a,0x6060606,0x63a063a,0x63a063a,0x66e063a,0x63a063a,0x66e066e,0x66e066e,0x240024,0x66e066e,0x240024,
0x5020502,0x5360502,0x5020502,0x5360536,0x5360536,0x56a056a,0x5360536,0x56a056a,0x56a056a,0x59e056a,0x56a056a,0x59e059e,0x59e059e,0x5d205d2,0x59e059e,0x5d205d2,
0x4320432,0x4660432,0x4320432,0x4660466,0x4660466,0x49a049a,0x4660466,0x49a049a,0x49a049a,0x4ce049a,0x49a049a,0x4ce04ce,0x4ce04ce,0x5020502,0x4ce04ce,0x5020502,
0x3620362,0x3960362,0x3620362,0x3960396,0x3960396,0x3ca03ca,0x3960396,0x3ca03ca,0x3ca03ca,0x3fe03ca,0x3ca03ca,0x3fe03fe,0x3fe03fe,0x4320432,0x3fe03fe,0x4320432,
0x2920292,0x2c60292,0x2920292,0x2c602c6,0x2c602c6,0x2fa02fa,0x2c602c6,0x2fa02fa,0x2fa02fa,0x32e02fa,0x2fa02fa,0x32e032e,0x32e032e,0x3620362,0x32e032e,0x3620362,
0x1c201c2,0x1f601c2,0x1c201c2,0x1f601f6,0x1f601f6,0x22a022a,0x1f601f6,0x22a022a,0x22a022a,0x25e022a,0x22a022a,0x25e025e,0x25e025e,0x2920292,0x25e025e,0x2920292,
0xf200f2,0x12600f2,0xf200f2,0x1260126,0x1260126,0x15a015a,0x1260126,0x15a015a,0x15a015a,0x18e015a,0x15a015a,0x18e018e,0x18e018e,0x1c201c2,0x18e018e,0x1c201c2,
0x220022,0x560022,0x220022,0x560056,0x560056,0x8a008a,0x560056,0x8a008a,0x8a008a,0xbe008a,0x8a008a,0xbe00be,0xbe00be,0xf200f2,0xbe00be,0xf200f2,
0x5d005d0,0x60405d0,0x5d005d0,0x6040604,0x6040604,0x6380638,0x6040604,0x6380638,0x6380638,0x66c0638,0x6380638,0x66c066c,0x66c066c,0x220022,0x66c066c,0x220022,
0x5000500,0x5340500,0x5000500,0x5340534,0x5340534,0x5680568,0x5340534,0x5680568,0x5680568,0x59c0568,0x5680568,0x59c059c,0x59c059c,0x5d005d0,0x59c059c,0x5d005d0,
0x4300430,0x4640430,0x4300430,0x4640464,0x4640464,0x4980498,0x4640464,0x4980498,0x4980498,0x4cc0498,0x4980498,0x4cc04cc,0x4cc04cc,0x5000500,0x4cc04cc,0x5000500,
0x3600360,0x3940360,0x3600360,0x3940394,0x3940394,0x3c803c8,0x3940394,0x3c803c8,0x3c803c8,0x3fc03c8,0x3c803c8,0x3fc03fc,0x3fc03fc,0x4300430,0x3fc03fc,0x4300430,
0x2900290,0x2c40290,0x2900290,0x2c402c4,0x2c402c4,0x2f802f8,0x2c402c4,0x2f802f8,0x2f802f8,0x32c02f8,0x2f802f8,0x32c032c,0x32c032c,0x3600360,0x32c032c,0x3600360,
0x1c001c0,0x1f401c0,0x1c001c0,0x1f401f4,0x1f401f4,0x2280228,0x1f401f4,0x2280228,0x2280228,0x25c0228,0x2280228,0x25c025c,0x25c025c,0x2900290,0x25c025c,0x2900290,
0xf000f0,0x12400f0,0xf000f0,0x1240124,0x1240124,0x1580158,0x1240124,0x1580158,0x1580158,0x18c0158,0x1580158,0x18c018c,0x18c018c,0x1c001c0,0x18c018c,0x1c001c0,
0x200020,0x540020,0x200020,0x540054,0x540054,0x880088,0x540054,0x880088,0x880088,0xbc0088,0x880088,0xbc00bc,0xbc00bc,0xf000f0,0xbc00bc,0xf000f0,
0x30003000,0x30003000,0x30003000,0x30003000,0x30003000,0x30003000,0x30003000,0x30003000,0x0,0x0,0x0,0x0,0x0,0x0,0x0,0x0,
0x30003000,0x30003000,0x30003000,0x30003000,0x30003000,0x30003000,0x30003000,0x30003000,0x0,0x0,0x0,0x0,0x0,0x0,0x0,0x0,
0x2a1f2da8,0xaf64ada8,0xaa1fada8,0x2f642da8,0x2f643000,0xaa1f0000,0xaf64b000,0x2a1f8000,0x2f642da8,0x2a1f2da8,0xaf64ada8,0xaa1fada8,0x2a1f0000,0x2f643000,0xaa1f0000,0xaf64b000,
0x263e2c72,0xafd9aea7,0xa63eac72,0x2fd92ea7,0x2ea72fd9,0xac72a63e,0xaea7afd9,0x2c72263e,0x2fd92ea7,0x263e2c72,0xafd9aea7,0xa63eac72,0x2c72263e,0x2ea72fd9,0xac72a63e,0xaea7afd9,
0x2da80000,0xada80000,0x2da88000,0xada80000,0x2da83000,0xada8b000,0x2da83000,0xada8b000,0x2da83000,0xada8b000,0x2da83000,0xada8b000,0xada80000,0x2da88000,0xada80000,0x2da88000,
0x2f642a1f,0xaf64aa1f,0x2f642a1f,0xaf64aa1f,0x2a1f2f64,0xaa1faf64,0x2a1f2f64,0xaa1faf64,0x2a1f2f64,0xaa1faf64,0x2a1f2f64,0xaa1faf64,0xaf64aa1f,0x2f642a1f,0xaf64aa1f,0x2f642a1f,
0xaa1f2da8,0x2f642da8,0x2a1fada8,0xaf64ada8,0x2f640000,0xaa1fb000,0xaf640000,0x2a1f3000,0xaf64ada8,0xaa1f2da8,0x2f642da8,0x2a1fada8,0x2a1f3000,0x2f648000,0xaa1fb000,0xaf640000,
0xaea7263e,0x2c722fd9,0x2ea7a63e,0xac72afd9,0x2fd92c72,0x263eaea7,0xafd9ac72,0xa63e2ea7,0xac72afd9,0xaea7263e,0x2c722fd9,0x2ea7a63e,0xa63e2ea7,0x2fd92c72,0x263eaea7,0xafd9ac72,
0xada82da8,0xada82da8,0xada82da8,0xada82da8,0x2da8ada8,0x2da8ada8,0x2da8ada8,0x2da8ada8,0x2da82da8,0x2da82da8,0x2da82da8,0x2da82da8,0xada8ada8,0xada8ada8,0xada8ada8,0xada8ada8,
0x3000,0x3000,0x3000,0x80003000,0x8000b000,0x8000b000,0x8000b000,0x8000b000,0x30000000,0x30008000,0x30008000,0x30008000,0xb0000000,0xb0000000,0xb0000000,0xb0000000,
0x2ea7263e,0xac722fd9,0xaea7a63e,0x2c72afd9,0xafd92c72,0xa63eaea7,0x2fd9ac72,0x263e2ea7,0x2c72afd9,0x2ea7263e,0xac722fd9,0xaea7a63e,0x263e2ea7,0xafd92c72,0xa63eaea7,0x2fd9ac72,
0x2f64ada8,0x2a1f2da8,0xaf642da8,0xaa1fada8,0xaa1f3000,0xaf640000,0x2a1fb000,0x2f648000,0xaa1fada8,0x2f64ada8,0x2a1f2da8,0xaf642da8,0x2f640000,0xaa1f3000,0xaf640000,0x2a1fb000,
0xaa1f2f64,0x2a1faf64,0xaa1f2f64,0x2a1faf64,0x2f64aa1f,0xaf642a1f,0x2f64aa1f,0xaf642a1f,0xaf642a1f,0x2f64aa1f,0xaf642a1f,0x2f64aa1f,0xaa1f2f64,0x2a1faf64,0xaa1f2f64,0x2a1faf64,
0x2da80000,0xada80000,0x2da88000,0xada80000,0x2da8b000,0xada83000,0x2da8b000,0xada83000,0xada83000,0x2da8b000,0xada83000,0x2da8b000,0x2da88000,0xada80000,0x2da88000,0xada88000,
0xa63e2c72,0x2fd9aea7,0x263eac72,0xafd92ea7,0xaea72fd9,0x2c72a63e,0x2ea7afd9,0xac72263e,0xafd92ea7,0xa63e2c72,0x2fd9aea7,0x263eac72,0xac72263e,0xaea72fd9,0x2c72a63e,0x2ea7afd9,
0x2f64ada8,0x2a1fada8,0xaf642da8,0xaa1f2da8,0x2a1f0000,0x2f64b000,0xaa1f0000,0xaf643000,0xaa1f2da8,0x2f64ada8,0x2a1fada8,0xaf642da8,0xaf643000,0x2a1f8000,0x2f64b000,0xaa1f8000,
0xb0003000,0xb0003000,0xb0003000,0xb0003000,0xb0003000,0xb0003000,0xb0003000,0xb0003000,0x0,0x8000,0x8000,0x80008000,0x8000,0x8000,0x8000,0x8000,
0x80000000,0x80000000,0x80008000,0x80008000,0x80000000,0x80008000,0x80008000,0x80008000,0xb0003000,0xb0003000,0xb0003000,0xb0003000,0xb0003000,0xb0003000,0xb0003000,0xb0003000,
0xaa1f2da8,0x2f64ada8,0x2a1fada8,0xaf642da8,0xaf643000,0x2a1f0000,0x2f64b000,0xaa1f8000,0xaf642da8,0xaa1f2da8,0x2f64ada8,0x2a1fada8,0xaa1f0000,0xaf643000,0x2a1f0000,0x2f64b000,
0x2fd9aea7,0x263eac72,0xafd92ea7,0xa63e2c72,0x2c72a63e,0x2ea7afd9,0xac72263e,0xaea72fd9,0xa63e2c72,0x2fd9aea7,0x263eac72,0xafd92ea7,0xaea72fd9,0x2c72a63e,0x2ea7afd9,0xac72263e,
0xada80000,0x2da80000,0xada88000,0x2da80000,0xada83000,0x2da8b000,0xada83000,0x2da8b000,0xada83000,0x2da8b000,0xada83000,0x2da8b000,0x2da80000,0xada88000,0x2da88000,0xada88000,
0xaa1f2f64,0x2a1faf64,0xaa1f2f64,0x2a1faf64,0x2f64aa1f,0xaf642a1f,0x2f64aa1f,0xaf642a1f,0x2f64aa1f,0xaf642a1f,0x2f64aa1f,0xaf642a1f,0x2a1faf64,0xaa1f2f64,0x2a1faf64,0xaa1f2f64,
0x2a1f2da8,0xaf642da8,0xaa1fada8,0x2f64ada8,0xaf640000,0x2a1fb000,0x2f640000,0xaa1f3000,0x2f64ada8,0x2a1f2da8,0xaf642da8,0xaa1fada8,0xaa1f3000,0xaf648000,0x2a1fb000,0x2f640000,
0x2c72afd9,0x2ea7263e,0xac722fd9,0xaea7a63e,0x263e2ea7,0xafd92c72,0xa63eaea7,0x2fd9ac72,0xaea7a63e,0x2c72afd9,0x2ea7263e,0xac722fd9,0x2fd9ac72,0x263e2ea7,0xafd92c72,0xa63eaea7,
0x2da8ada8,0x2da8ada8,0x2da8ada8,0x2da8ada8,0xada82da8,0xada82da8,0xada82da8,0xada82da8,0x2da82da8,0x2da82da8,0x2da82da8,0x2da82da8,0xada8ada8,0xada8ada8,0xada8ada8,0xada8ada8,
0x80003000,0x80003000,0x80003000,0x3000,0xb000,0x8000b000,0xb000,0xb000,0xb0000000,0xb0008000,0xb0008000,0xb0008000,0x30000000,0x30000000,0x30000000,0x30008000,
0x2c722fd9,0x2ea7a63e,0xac72afd9,0xaea7263e,0x263eaea7,0xafd9ac72,0xa63e2ea7,0x2fd92c72,0xaea7263e,0x2c722fd9,0x2ea7a63e,0xac72afd9,0x2fd92c72,0x263eaea7,0xafd9ac72,0xa63e2ea7,
0xaf64ada8,0xaa1f2da8,0x2f642da8,0x2a1fada8,0x2a1f3000,0x2f648000,0xaa1fb000,0xaf648000,0x2a1fada8,0xaf64ada8,0xaa1f2da8,0x2f642da8,0xaf640000,0x2a1f3000,0x2f648000,0xaa1fb000,
0x2f642a1f,0xaf64aa1f,0x2f642a1f,0xaf64aa1f,0x2a1f2f64,0xaa1faf64,0x2a1f2f64,0xaa1faf64,0xaa1faf64,0x2a1f2f64,0xaa1faf64,0x2a1f2f64,0x2f642a1f,0xaf64aa1f,0x2f642a1f,0xaf64aa1f,
0xada80000,0x2da80000,0xada88000,0x2da88000,0xada8b000,0x2da83000,0xada8b000,0x2da83000,0x2da83000,0xada8b000,0x2da83000,0xada8b000,0xada88000,0x2da88000,0xada88000,0x2da80000,
0x2fd92ea7,0x263e2c72,0xafd9aea7,0xa63eac72,0x2c72263e,0x2ea72fd9,0xac72a63e,0xaea7afd9,0xa63eac72,0x2fd92ea7,0x263e2c72,0xafd9aea7,0xaea7afd9,0x2c72263e,0x2ea72fd9,0xac72a63e,
0xaf64ada8,0xaa1fada8,0x2f642da8,0x2a1f2da8,0xaa1f0000,0xaf64b000,0x2a1f0000,0x2f643000,0x2a1f2da8,0xaf64ada8,0xaa1fada8,0x2f642da8,0x2f643000,0xaa1f8000,0xaf64b000,0x2a1f0000,
0x80008000,0x80008000,0x80008000,0x80008000,0x80008000,0x80008000,0x80008000,0x80008000,0x30003000,0x30003000,0x30003000,0x30003000,0x30003000,0x30003000,0x30003000,0x30003000,
0x80008000,0x80008000,0x80008000,0x80008000,0x80008000,0x80008000,0x80008000,0x80008000,0x30003000,0x30003000,0x30003000,0x30003000,0x30003000,0x30003000,0x30003000,0x30003000,
0xaf64ada8,0xaa1fada8,0x2f642da8,0x2a1f2da8,0xaa1f8000,0xaf64b000,0x2a1f8000,0x2f643000,0x2a1f2da8,0xaf64ada8,0xaa1fada8,0x2f642da8,0x2f643000,0xaa1f0000,0xaf64b000,0x2a1f8000,
0xafd9aea7,0xa63eac72,0x2fd92ea7,0x263e2c72,0xac72a63e,0xaea7afd9,0x2c72263e,0x2ea72fd9,0x263e2c72,0xafd9aea7,0xa63eac72,0x2fd92ea7,0x2ea72fd9,0xac72a63e,0xaea7afd9,0x2c72263e,
0x2da83000,0xada8b000,0x2da83000,0xada8b000,0xada80000,0x2da88000,0xada80000,0x2da88000,0xada88000,0x2da88000,0xada80000,0x2da88000,0xada8b000,0x2da83000,0xada8b000,0x2da83000,
0x2a1f2f64,0xaa1faf64,0x2a1f2f64,0xaa1faf64,0xaf64aa1f,0x2f642a1f,0xaf64aa1f,0x2f642a1f,0xaf64aa1f,0x2f642a1f,0xaf64aa1f,0x2f642a1f,0xaa1faf64,0x2a1f2f64,0xaa1faf64,0x2a1f2f64,
0xaf64ada8,0xaa1f2da8,0x2f642da8,0x2a1fada8,0x2a1f3000,0x2f648000,0xaa1fb000,0xaf640000,0x2a1fada8,0xaf64ada8,0xaa1f2da8,0x2f642da8,0xaf648000,0x2a1f3000,0x2f648000,0xaa1fb000,
0xac72afd9,0xaea7263e,0x2c722fd9,0x2ea7a63e,0xa63e2ea7,0x2fd92c72,0x263eaea7,0xafd9ac72,0x2ea7a63e,0xac72afd9,0xaea7263e,0x2c722fd9,0xafd9ac72,0xa63e2ea7,0x2fd92c72,0x263eaea7,
0xada8ada8,0xada8ada8,0xada8ada8,0xada8ada8,0x2da82da8,0x2da82da8,0x2da82da8,0x2da82da8,0xada82da8,0xada82da8,0xada82da8,0xada82da8,0x2da8ada8,0x2da8ada8,0x2da8ada8,0x2da8ada8,
0xb0008000,0xb0000000,0xb0000000,0xb0000000,0x30008000,0x30008000,0x30008000,0x30008000,0x3000,0x3000,0x3000,0x80003000,0x8000b000,0x8000b000,0x8000b000,0x8000b000,
0xac722fd9,0xaea7a63e,0x2c72afd9,0x2ea7263e,0xa63eaea7,0x2fd9ac72,0x263e2ea7,0xafd92c72,0x2ea7263e,0xac722fd9,0xaea7a63e,0x2c72afd9,0xafd92c72,0xa63eaea7,0x2fd9ac72,0x263e2ea7,
0x2a1f2da8,0xaf642da8,0xaa1fada8,0x2f64ada8,0xaf648000,0x2a1fb000,0x2f648000,0xaa1f3000,0x2f64ada8,0x2a1f2da8,0xaf642da8,0xaa1fada8,0xaa1f3000,0xaf640000,0x2a1fb000,0x2f648000,
0xaf642a1f,0x2f64aa1f,0xaf642a1f,0x2f64aa1f,0xaa1f2f64,0x2a1faf64,0xaa1f2f64,0x2a1faf64,0x2a1faf64,0xaa1f2f64,0x2a1faf64,0xaa1f2f64,0xaf642a1f,0x2f64aa1f,0xaf642a1f,0x2f64aa1f,
0xada83000,0x2da8b000,0xada83000,0x2da8b000,0x2da88000,0xada80000,0x2da88000,0xada88000,0xada88000,0x2da88000,0xada80000,0x2da88000,0xada83000,0x2da8b000,0xada83000,0x2da8b000,
0xafd92ea7,0xa63e2c72,0x2fd9aea7,0x263eac72,0xac72263e,0xaea72fd9,0x2c72a63e,0x2ea7afd9,0x263eac72,0xafd92ea7,0xa63e2c72,0x2fd9aea7,0x2ea7afd9,0xac72263e,0xaea72fd9,0x2c72a63e,
0xaa1f2da8,0x2f64ada8,0x2a1fada8,0xaf642da8,0xaf643000,0x2a1f8000,0x2f64b000,0xaa1f8000,0xaf642da8,0xaa1f2da8,0x2f64ada8,0x2a1fada8,0xaa1f8000,0xaf643000,0x2a1f8000,0x2f64b000,
0x80008000,0x80000000,0x80000000,0x0,0x80000000,0x80000000,0x80000000,0x80000000,0xb0003000,0xb0003000,0xb0003000,0xb0003000,0xb0003000,0xb0003000,0xb0003000,0xb0003000,
0x3000b000,0x3000b000,0x3000b000,0x3000b000,0x3000b000,0x3000b000,0x3000b000,0x3000b000,0x80000000,0x80000000,0x80008000,0x80008000,0x80000000,0x80008000,0x80008000,0x80008000,
0x2f64ada8,0x2a1fada8,0xaf642da8,0xaa1f2da8,0x2a1f8000,0x2f64b000,0xaa1f8000,0xaf643000,0xaa1f2da8,0x2f64ada8,0x2a1fada8,0xaf642da8,0xaf643000,0x2a1f0000,0x2f64b000,0xaa1f8000,
0x263eac72,0xafd92ea7,0xa63e2c72,0x2fd9aea7,0x2ea7afd9,0xac72263e,0xaea72fd9,0x2c72a63e,0x2fd9aea7,0x263eac72,0xafd92ea7,0xa63e2c72,0x2c72a63e,0x2ea7afd9,0xac72263e,0xaea72fd9,
0xada83000,0x2da8b000,0xada83000,0x2da8b000,0x2da80000,0xada88000,0x2da88000,0xada88000,0x2da88000,0xada88000,0x2da80000,0xada88000,0x2da8b000,0xada83000,0x2da8b000,0xada83000,
0x2f64aa1f,0xaf642a1f,0x2f64aa1f,0xaf642a1f,0x2a1faf64,0xaa1f2f64,0x2a1faf64,0xaa1f2f64,0x2a1faf64,0xaa1f2f64,0x2a1faf64,0xaa1f2f64,0xaf642a1f,0x2f64aa1f,0xaf642a1f,0x2f64aa1f,
0x2f64ada8,0x2a1f2da8,0xaf642da8,0xaa1fada8,0xaa1f3000,0xaf648000,0x2a1fb000,0x2f640000,0xaa1fada8,0x2f64ada8,0x2a1f2da8,0xaf642da8,0x2f648000,0xaa1f3000,0xaf648000,0x2a1fb000,
0xaea7a63e,0x2c72afd9,0x2ea7263e,0xac722fd9,0x2fd9ac72,0x263e2ea7,0xafd92c72,0xa63eaea7,0xac722fd9,0xaea7a63e,0x2c72afd9,0x2ea7263e,0xa63eaea7,0x2fd9ac72,0x263e2ea7,0xafd92c72,
0xada8ada8,0xada8ada8,0xada8ada8,0xada8ada8,0x2da82da8,0x2da82da8,0x2da82da8,0x2da82da8,0x2da8ada8,0x2da8ada8,0x2da8ada8,0x2da8ada8,0xada82da8,0xada82da8,0xada82da8,0xada82da8,
0x30008000,0x30000000,0x30000000,0x30000000,0xb0008000,0xb0008000,0xb0008000,0xb0000000,0x80003000,0x80003000,0x80003000,0x3000,0xb000,0x8000b000,0xb000,0xb000,
0x2ea7a63e,0xac72afd9,0xaea7263e,0x2c722fd9,0xafd9ac72,0xa63e2ea7,0x2fd92c72,0x263eaea7,0x2c722fd9,0x2ea7a63e,0xac72afd9,0xaea7263e,0x263eaea7,0xafd9ac72,0xa63e2ea7,0x2fd92c72,
0xaa1f2da8,0x2f642da8,0x2a1fada8,0xaf64ada8,0x2f648000,0xaa1fb000,0xaf640000,0x2a1f3000,0xaf64ada8,0xaa1f2da8,0x2f642da8,0x2a1fada8,0x2a1f3000,0x2f648000,0xaa1fb000,0xaf648000,
0xaa1faf64,0x2a1f2f64,0xaa1faf64,0x2a1f2f64,0x2f642a1f,0xaf64aa1f,0x2f642a1f,0xaf64aa1f,0xaf64aa1f,0x2f642a1f,0xaf64aa1f,0x2f642a1f,0xaa1faf64,0x2a1f2f64,0xaa1faf64,0x2a1f2f64,
0x2da83000,0xada8b000,0x2da83000,0xada8b000,0xada88000,0x2da88000,0xada88000,0x2da80000,0x2da88000,0xada88000,0x2da80000,0xada80000,0x2da83000,0xada8b000,0x2da83000,0xada8b000,
0xa63eac72,0x2fd92ea7,0x263e2c72,0xafd9aea7,0xaea7afd9,0x2c72263e,0x2ea72fd9,0xac72a63e,0xafd9aea7,0xa63eac72,0x2fd92ea7,0x263e2c72,0xac72a63e,0xaea7afd9,0x2c72263e,0x2ea72fd9,
0x2a1f2da8,0xaf64ada8,0xaa1fada8,0x2f642da8,0x2f643000,0xaa1f8000,0xaf64b000,0x2a1f0000,0x2f642da8,0x2a1f2da8,0xaf64ada8,0xaa1fada8,0x2a1f8000,0x2f643000,0xaa1f8000,0xaf64b000,
0x3c003c00,0x3c003c00,0x3c003c00,0x3c003c00,0x3c003c00,0x3c003c00,0x3c003c00,0x3c003c00,0x80008000,0x80008000,0x80008000,0x80008000,0x80008000,0x80008000,0x80008000,0x80008000,
0x3bd93c00,0x3aa73b64,0x387239a8,0x323e361f,0xb23e0000,0xb872b61f,0xbaa7b9a8,0xbbd9bb64,0xb23e8000,0xb872b61f,0xbaa7b9a8,0xbbd9bb64,0xbbd9bc00,0xbaa7bb64,0xb872b9a8,0xb23eb61f,
0xbb64bc00,0xb61fb9a8,0x361f8000,0x3b6439a8,0x3b643c00,0x361f39a8,0xb61f0000,0xbb64b9a8,0x361f8000,0x3b6439a8,0x3b643c00,0x361f39a8,0xb61f8000,0xbb64b9a8,0xbb64bc00,0xb61fb9a8,
0x38728000,0x3bd93b64,0x323e39a8,0xbaa7b61f,0x3aa73c00,0xb23e361f,0xbbd9b9a8,0xb872bb64,0x3aa73c00,0xb23e361f,0xbbd9b9a8,0xb872bb64,0xb8728000,0xbbd9bb64,0xb23eb9a8,0x3aa7361f,
0xbc008000,0x3c008000,0xbc000000,0x3c008000,0xbc000000,0x3c008000,0xbc000000,0x3c008000,0x3c00,0x8000bc00,0x3c00,0x8000bc00,0x3c00,0x8000bc00,0x80003c00,0x8000bc00,
0xbbd98000,0x3aa7361f,0xb872b9a8,0x323e3b64,0x323ebc00,0xb8723b64,0x3aa7b9a8,0xbbd9361f,0xb23e3c00,0x3872bb64,0xbaa739a8,0x3bd9b61f,0xbbd90000,0x3aa7361f,0xb872b9a8,0x323e3b64,
0x3b648000,0xb61fb9a8,0xb61f3c00,0x3b64b9a8,0xbb648000,0x361f39a8,0x361fbc00,0xbb6439a8,0x361fbc00,0xbb6439a8,0x3b648000,0xb61fb9a8,0xb61f3c00,0x3b64b9a8,0xbb640000,0x361f39a8,
0xb8723c00,0x3bd9b61f,0xb23eb9a8,0xbaa73b64,0xbaa78000,0xb23e3b64,0x3bd9b9a8,0xb872b61f,0x3aa78000,0x323ebb64,0xbbd939a8,0x3872361f,0xb8723c00,0x3bd9b61f,0xb23eb9a8,0xbaa73b64,
0xbbd93c00,0xbaa73b64,0xb87239a8,0xb23e361f,0x323e8000,0x3872b61f,0x3aa7b9a8,0x3bd9bb64,0x323e8000,0x3872b61f,0x3aa7b9a8,0x3bd9bb64,0x3bd9bc00,0x3aa7bb64,0x3872b9a8,0x323eb61f,
0xbc003c00,0xbc003c00,0xbc003c00,0xbc003c00,0xbc003c00,0xbc003c00,0xbc003c00,0xbc003c00,0x80008000,0x80000000,0x80000000,0x80000000,0x80000000,0x80000000,0x0,0x80000000,
0xb8728000,0xbbd93b64,0xb23e39a8,0x3aa7b61f,0xbaa73c00,0x323e361f,0x3bd9b9a8,0x3872bb64,0xbaa73c00,0x323e361f,0x3bd9b9a8,0x3872bb64,0x38728000,0x3bd9bb64,0x323eb9a8,0xbaa7361f,
0x3b64bc00,0x361fb9a8,0xb61f8000,0xbb6439a8,0xbb643c00,0xb61f39a8,0x361f0000,0x3b64b9a8,0xb61f8000,0xbb6439a8,0xbb643c00,0xb61f39a8,0x361f8000,0x3b64b9a8,0x3b64bc00,0x361fb9a8,
0x3bd98000,0xbaa7361f,0x3872b9a8,0xb23e3b64,0xb23ebc00,0x38723b64,0xbaa7b9a8,0x3bd9361f,0x323e3c00,0xb872bb64,0x3aa739a8,0xbbd9b61f,0x3bd98000,0xbaa7361f,0x3872b9a8,0xb23e3b64,
0x3c008000,0xbc008000,0x3c000000,0xbc008000,0x3c000000,0xbc008000,0x3c000000,0xbc000000,0x80003c00,0xbc00,0x80003c00,0x8000bc00,0x80003c00,0xbc00,0x80003c00,0xbc00,
0x38723c00,0xbbd9b61f,0x323eb9a8,0x3aa73b64,0x3aa78000,0x323e3b64,0xbbd9b9a8,0x3872b61f,0xbaa78000,0xb23ebb64,0x3bd939a8,0xb872361f,0x38723c00,0xbbd9b61f,0x323eb9a8,0x3aa73b64,
0xbb640000,0x361fb9a8,0x361f3c00,0xbb64b9a8,0x3b648000,0xb61f39a8,0xb61fbc00,0x3b6439a8,0xb61fbc00,0x3b6439a8,0xbb640000,0x361fb9a8,0x361f3c00,0xbb64b9a8,0x3b648000,0xb61f39a8,
0x39a83c00,0xb9a80000,0xb9a8bc00,0x39a88000,0x39a83c00,0xb9a80000,0xb9a8bc00,0x39a88000,0xb9a88000,0xb9a8bc00,0x39a88000,0x39a83c00,0xb9a80000,0xb9a8bc00,0x39a88000,0x39a83c00,
0x38723c00,0xbbd9b61f,0x323eb9a8,0x3aa73b64,0xbaa70000,0xb23ebb64,0x3bd939a8,0xb872361f,0xbaa78000,0xb23ebb64,0x3bd939a8,0xb872361f,0xb872bc00,0x3bd9361f,0xb23e39a8,0xbaa7bb64,
0xb61fbc00,0x3b6439a8,0xbb640000,0x361fb9a8,0x361f3c00,0xbb64b9a8,0x3b648000,0xb61f39a8,0x3b648000,0xb61f39a8,0xb61fbc00,0x3b6439a8,0xbb648000,0x361fb9a8,0x361f3c00,0xbb64b9a8,
0x3bd98000,0xbaa7361f,0x3872b9a8,0xb23e3b64,0x323e3c00,0xb872bb64,0x3aa739a8,0xbbd9b61f,0x323e3c00,0xb872bb64,0x3aa739a8,0xbbd9b61f,0xbbd98000,0x3aa7b61f,0xb87239a8,0x323ebb64,
0xb9a88000,0xb9a83c00,0x39a88000,0x39a8bc00,0xb9a80000,0xb9a83c00,0x39a88000,0x39a8bc00,0xb9a83c00,0x39a88000,0x39a8bc00,0xb9a80000,0xb9a83c00,0x39a88000,0x39a8bc00,0xb9a88000,
0xb8728000,0xbbd93b64,0xb23e39a8,0x3aa7b61f,0x3aa7bc00,0xb23eb61f,0xbbd939a8,0xb8723b64,0xbaa73c00,0x323e361f,0x3bd9b9a8,0x3872bb64,0xb8728000,0xbbd93b64,0xb23e39a8,0x3aa7b61f,
0x361f8000,0x3b64b9a8,0x3b64bc00,0x361fb9a8,0xb61f8000,0xbb6439a8,0xbb643c00,0xb61f39a8,0x3b64bc00,0x361fb9a8,0xb61f8000,0xbb6439a8,0xbb643c00,0xb61f39a8,0x361f8000,0x3b64b9a8,
0xbbd93c00,0xbaa73b64,0xb87239a8,0xb23e361f,0xb23e8000,0xb872361f,0xbaa739a8,0xbbd93b64,0x323e8000,0x3872b61f,0x3aa7b9a8,0x3bd9bb64,0xbbd93c00,0xbaa73b64,0xb87239a8,0xb23e361f,
0xb8723c00,0x3bd9b61f,0xb23eb9a8,0xbaa73b64,0x3aa78000,0x323ebb64,0xbbd939a8,0x3872361f,0x3aa78000,0x323ebb64,0xbbd939a8,0x3872361f,0x3872bc00,0xbbd9361f,0x323e39a8,0x3aa7bb64,
0xb9a83c00,0x39a80000,0x39a8bc00,0xb9a88000,0xb9a83c00,0x39a88000,0x39a8bc00,0xb9a88000,0x39a88000,0x39a8bc00,0xb9a88000,0xb9a83c00,0x39a80000,0x39a8bc00,0xb9a88000,0xb9a83c00,
0xbbd98000,0x3aa7361f,0xb872b9a8,0x323e3b64,0xb23e3c00,0x3872bb64,0xbaa739a8,0x3bd9b61f,0xb23e3c00,0x3872bb64,0xbaa739a8,0x3bd9b61f,0x3bd98000,0xbaa7b61f,0x387239a8,0xb23ebb64,
0x361fbc00,0xbb6439a8,0x3b640000,0xb61fb9a8,0xb61f3c00,0x3b64b9a8,0xbb648000,0x361f39a8,0xbb648000,0x361f39a8,0x361fbc00,0xbb6439a8,0x3b648000,0xb61fb9a8,0xb61f3c00,0x3b64b9a8,
0x38728000,0x3bd93b64,0x323e39a8,0xbaa7b61f,0xbaa7bc00,0x323eb61f,0x3bd939a8,0x38723b64,0x3aa73c00,0xb23e361f,0xbbd9b9a8,0xb872bb64,0x38728000,0x3bd93b64,0x323e39a8,0xbaa7b61f,
0x39a88000,0x39a83c00,0xb9a88000,0xb9a8bc00,0x39a80000,0x39a83c00,0xb9a80000,0xb9a8bc00,0x39a83c00,0xb9a88000,0xb9a8bc00,0x39a88000,0x39a83c00,0xb9a88000,0xb9a8bc00,0x39a80000,
0x3bd93c00,0x3aa73b64,0x387239a8,0x323e361f,0x323e8000,0x3872361f,0x3aa739a8,0x3bd93b64,0xb23e8000,0xb872b61f,0xbaa7b9a8,0xbbd9bb64,0x3bd93c00,0x3aa73b64,0x387239a8,0x323e361f,
0xb61f8000,0xbb64b9a8,0xbb64bc00,0xb61fb9a8,0x361f8000,0x3b6439a8,0x3b643c00,0x361f39a8,0xbb64bc00,0xb61fb9a8,0x361f0000,0x3b6439a8,0x3b643c00,0x361f39a8,0xb61f8000,0xbb64b9a8,
0x0,0x0,0x0,0x0,0x0,0x0,0x0,0x0,0x3c003c00,0x3c003c00,0x3c003c00,0x3c003c00,0x3c003c00,0x3c003c00,0x3c003c00,0x3c003c00,
0x323e0000,0x3872361f,0x3aa739a8,0x3bd93b64,0x3bd93c00,0x3aa73b64,0x387239a8,0x323e361f,0x3bd93c00,0x3aa73b64,0x387239a8,0x323e361f,0xb23e0000,0xb872b61f,0xbaa7b9a8,0xbbd9bb64,
0xb61f0000,0xbb64b9a8,0xbb64bc00,0xb61fb9a8,0x361f0000,0x3b6439a8,0x3b643c00,0x361f39a8,0xbb64bc00,0xb61fb9a8,0x361f8000,0x3b6439a8,0x3b643c00,0x361f39a8,0xb61f0000,0xbb64b9a8,
0xbaa7bc00,0x323eb61f,0x3bd939a8,0x38723b64,0x38720000,0x3bd93b64,0x323e39a8,0xbaa7b61f,0x38728000,0x3bd93b64,0x323e39a8,0xbaa7b61f,0x3aa73c00,0xb23e361f,0xbbd9b9a8,0xb872bb64,
0x3c00,0x8000bc00,0x3c00,0x8000bc00,0x3c00,0x8000bc00,0x80003c00,0x8000bc00,0x3c000000,0xbc000000,0x3c008000,0xbc000000,0x3c008000,0xbc000000,0x3c008000,0xbc000000,
0xb23e3c00,0x3872bb64,0xbaa739a8,0x3bd9b61f,0xbbd90000,0x3aa7361f,0xb872b9a8,0x323e3b64,0x3bd90000,0xbaa7b61f,0x387239a8,0xb23ebb64,0xb23e3c00,0x3872bb64,0xbaa739a8,0x3bd9b61f,
0x361fbc00,0xbb6439a8,0x3b648000,0xb61fb9a8,0xb61f3c00,0x3b64b9a8,0xbb640000,0x361f39a8,0xbb640000,0x361f39a8,0x361fbc00,0xbb6439a8,0x3b640000,0xb61fb9a8,0xb61f3c00,0x3b64b9a8,
0x3aa78000,0x323ebb64,0xbbd939a8,0x3872361f,0xb8723c00,0x3bd9b61f,0xb23eb9a8,0xbaa73b64,0x3872bc00,0xbbd9361f,0x323e39a8,0x3aa7bb64,0x3aa70000,0x323ebb64,0xbbd939a8,0x3872361f,
0xb23e0000,0xb872361f,0xbaa739a8,0xbbd93b64,0xbbd93c00,0xbaa73b64,0xb87239a8,0xb23e361f,0xbbd93c00,0xbaa73b64,0xb87239a8,0xb23e361f,0x323e8000,0x3872b61f,0x3aa7b9a8,0x3bd9bb64,
0x0,0x8000,0x8000,0x8000,0x8000,0x8000,0x80008000,0x8000,0xbc003c00,0xbc003c00,0xbc003c00,0xbc003c00,0xbc003c00,0xbc003c00,0xbc003c00,0xbc003c00,
0x3aa7bc00,0xb23eb61f,0xbbd939a8,0xb8723b64,0xb8720000,0xbbd93b64,0xb23e39a8,0x3aa7b61f,0xb8728000,0xbbd93b64,0xb23e39a8,0x3aa7b61f,0xbaa73c00,0x323e361f,0x3bd9b9a8,0x3872bb64,
0x361f0000,0x3b64b9a8,0x3b64bc00,0x361fb9a8,0xb61f0000,0xbb6439a8,0xbb643c00,0xb61f39a8,0x3b64bc00,0x361fb9a8,0xb61f8000,0xbb6439a8,0xbb643c00,0xb61f39a8,0x361f0000,0x3b64b9a8,
0x323e3c00,0xb872bb64,0x3aa739a8,0xbbd9b61f,0x3bd98000,0xbaa7361f,0x3872b9a8,0xb23e3b64,0xbbd90000,0x3aa7b61f,0xb87239a8,0x323ebb64,0x323e3c00,0xb872bb64,0x3aa739a8,0xbbd9b61f,
0x80003c00,0xbc00,0x80003c00,0x8000bc00,0x80003c00,0xbc00,0x80003c00,0xbc00,0xbc000000,0x3c000000,0xbc008000,0x3c000000,0xbc008000,0x3c000000,0xbc008000,0x3c008000,
0xbaa78000,0xb23ebb64,0x3bd939a8,0xb872361f,0x38723c00,0xbbd9b61f,0x323eb9a8,0x3aa73b64,0xb872bc00,0x3bd9361f,0xb23e39a8,0xbaa7bb64,0xbaa70000,0xb23ebb64,0x3bd939a8,0xb872361f,
0xb61fbc00,0x3b6439a8,0xbb640000,0x361fb9a8,0x361f3c00,0xbb64b9a8,0x3b648000,0xb61f39a8,0x3b648000,0xb61f39a8,0xb61fbc00,0x3b6439a8,0xbb640000,0x361fb9a8,0x361f3c00,0xbb64b9a8,
0x39a80000,0x39a83c00,0xb9a80000,0xb9a8bc00,0x39a88000,0x39a83c00,0xb9a80000,0xb9a8bc00,0x39a83c00,0xb9a80000,0xb9a8bc00,0x39a88000,0x39a83c00,0xb9a80000,0xb9a8bc00,0x39a88000,
0x3aa70000,0x323e3b64,0xbbd9b9a8,0x3872b61f,0x38723c00,0xbbd9b61f,0x323eb9a8,0x3aa73b64,0x38723c00,0xbbd9b61f,0x323eb9a8,0x3aa73b64,0xbaa70000,0xb23ebb64,0x3bd939a8,0xb872361f,
0xbb640000,0x361fb9a8,0x361f3c00,0xbb64b9a8,0x3b640000,0xb61f39a8,0xb61fbc00,0x3b6439a8,0xb61fbc00,0x3b6439a8,0xbb640000,0x361fb9a8,0x361f3c00,0xbb64b9a8,0x3b648000,0xb61f39a8,
0xb23ebc00,0x38723b64,0xbaa7b9a8,0x3bd9361f,0x3bd90000,0xbaa7361f,0x3872b9a8,0xb23e3b64,0x3bd98000,0xbaa7361f,0x3872b9a8,0xb23e3b64,0x323e3c00,0xb872bb64,0x3aa739a8,0xbbd9b61f,
0xb9a83c00,0x39a88000,0x39a8bc00,0xb9a80000,0xb9a83c00,0x39a88000,0x39a8bc00,0xb9a88000,0x39a80000,0x39a8bc00,0xb9a80000,0xb9a83c00,0x39a88000,0x39a8bc00,0xb9a80000,0xb9a83c00,
0xbaa73c00,0x323e361f,0x3bd9b9a8,0x3872bb64,0xb8728000,0xbbd93b64,0xb23e39a8,0x3aa7b61f,0x38720000,0x3bd9bb64,0x323eb9a8,0xbaa7361f,0xbaa73c00,0x323e361f,0x3bd9b9a8,0x3872bb64,
0x3b64bc00,0x361fb9a8,0xb61f8000,0xbb6439a8,0xbb643c00,0xb61f39a8,0x361f8000,0x3b64b9a8,0xb61f0000,0xbb6439a8,0xbb643c00,0xb61f39a8,0x361f0000,0x3b64b9a8,0x3b64bc00,0x361fb9a8,
0x323e8000,0x3872b61f,0x3aa7b9a8,0x3bd9bb64,0xbbd93c00,0xbaa73b64,0xb87239a8,0xb23e361f,0x3bd9bc00,0x3aa7bb64,0x3872b9a8,0x323eb61f,0x323e0000,0x3872b61f,0x3aa7b9a8,0x3bd9bb64,
0xbaa70000,0xb23e3b64,0x3bd9b9a8,0xb872b61f,0xb8723c00,0x3bd9b61f,0xb23eb9a8,0xbaa73b64,0xb8723c00,0x3bd9b61f,0xb23eb9a8,0xbaa73b64,0x3aa78000,0x323ebb64,0xbbd939a8,0x3872361f,
0xb9a80000,0xb9a83c00,0x39a80000,0x39a8bc00,0xb9a88000,0xb9a83c00,0x39a80000,0x39a8bc00,0xb9a83c00,0x39a80000,0x39a8bc00,0xb9a88000,0xb9a83c00,0x39a88000,0x39a8bc00,0xb9a88000,
0x323ebc00,0xb8723b64,0x3aa7b9a8,0xbbd9361f,0xbbd90000,0x3aa7361f,0xb872b9a8,0x323e3b64,0xbbd98000,0x3aa7361f,0xb872b9a8,0x323e3b64,0xb23e3c00,0x3872bb64,0xbaa739a8,0x3bd9b61f,
0x3b640000,0xb61fb9a8,0xb61f3c00,0x3b64b9a8,0xbb640000,0x361f39a8,0x361fbc00,0xbb6439a8,0x361fbc00,0xbb6439a8,0x3b640000,0xb61fb9a8,0xb61f3c00,0x3b64b9a8,0xbb648000,0x361f39a8,
0x3aa73c00,0xb23e361f,0xbbd9b9a8,0xb872bb64,0x38728000,0x3bd93b64,0x323e39a8,0xbaa7b61f,0xb8720000,0xbbd9bb64,0xb23eb9a8,0x3aa7361f,0x3aa73c00,0xb23e361f,0xbbd9b9a8,0xb872bb64,
0x39a83c00,0xb9a88000,0xb9a8bc00,0x39a88000,0x39a83c00,0xb9a88000,0xb9a8bc00,0x39a80000,0xb9a80000,0xb9a8bc00,0x39a80000,0x39a83c00,0xb9a88000,0xb9a8bc00,0x39a88000,0x39a83c00,
0xb23e8000,0xb872b61f,0xbaa7b9a8,0xbbd9bb64,0x3bd93c00,0x3aa73b64,0x387239a8,0x323e361f,0xbbd9bc00,0xbaa7bb64,0xb872b9a8,0xb23eb61f,0xb23e0000,0xb872b61f,0xbaa7b9a8,0xbbd9bb64,
0xbb64bc00,0xb61fb9a8,0x361f0000,0x3b6439a8,0x3b643c00,0x361f39a8,0xb61f8000,0xbb64b9a8,0x361f0000,0x3b6439a8,0x3b643c00,0x361f39a8,0xb61f0000,0xbb64b9a8,0xbb64bc00,0xb61fb9a8,
};
__device__ __align__(1024) bf16 g_x1T[DM * XP];
__device__ __align__(1024) bf16 g_x2T[DM * XP];
__device__ __align__(1024) uint4 g_of[8][16][1280];
__device__ __align__(1024) float g_fs[2][SEQ];

#define TS_SMEM 0
#define TS_DECL
#define TS_ARG
#define TS_PASS
#define TS_PHASE(p)
#define TS(i)
#define TSX(row, i)
#define TS_BEGIN
#define TS_END

struct cplx { float r, i; };
__device__ __forceinline__ cplx cmul(cplx a, cplx b) {
    cplx o;
    o.r = fmaf(a.r, b.r, -a.i * b.i);
    o.i = fmaf(a.r, b.i, a.i * b.r);
    return o;
}
__device__ __forceinline__ cplx csq(cplx a) {
    cplx o;
    o.r = fmaf(a.r, a.r, -a.i * a.i);
    o.i = 2.f * a.r * a.i;
    return o;
}
__device__ __forceinline__ cplx cexp_p(float arl, float ai, float p) {
    float mag = ex2(arl * p);
    float ang = ai * p;
    float n = rintf(ang * 0.15915494309189535f);
    float r = fmaf(n, -6.2831854820251465f, ang);
    r = fmaf(n, 1.7484555e-7f, r);
    cplx o;
    o.r = mag * __cosf(r);
    o.i = mag * __sinf(r);
    return o;
}

__device__ __forceinline__ uint32_t pack2h(float lo, float hi) {
    uint32_t r;
    asm("cvt.rn.f16x2.f32 %0, %1, %2;" : "=r"(r) : "f"(hi), "f"(lo));
    return r;
}
__device__ __forceinline__ uint32_t hmul(uint32_t a, uint32_t b) { uint32_t d; asm("mul.rn.f16x2 %0, %1, %2;" : "=r"(d) : "r"(a), "r"(b)); return d; }
__device__ __forceinline__ uint32_t hfma(uint32_t a, uint32_t b, uint32_t c) { uint32_t d; asm("fma.rn.f16x2 %0, %1, %2, %3;" : "=r"(d) : "r"(a), "r"(b), "r"(c)); return d; }
__device__ __forceinline__ uint32_t hfms(uint32_t a, uint32_t b, uint32_t c) {
    uint32_t d;
    asm("{\n.reg .b32 n;\nneg.f16x2 n, %1;\nfma.rn.f16x2 %0, n, %2, %3;\n}" : "=r"(d) : "r"(a), "r"(b), "r"(c));
    return d;
}
__device__ __forceinline__ uint32_t hadd(uint32_t a, uint32_t b) { uint32_t d; asm("add.rn.f16x2 %0, %1, %2;" : "=r"(d) : "r"(a), "r"(b)); return d; }
__device__ __forceinline__ uint32_t hsub(uint32_t a, uint32_t b) { uint32_t d; asm("sub.rn.f16x2 %0, %1, %2;" : "=r"(d) : "r"(a), "r"(b)); return d; }
__device__ __forceinline__ uint4 ldg_tab(int tab, int t) { return ldg128((const uint4*)c_fft + t + tab * 128); }
__device__ __forceinline__ uint32_t u4(const uint4& v, int i) { return i == 0 ? v.x : i == 1 ? v.y : i == 2 ? v.z : v.w; }
struct cpair { uint32_t r, i; };
__device__ __forceinline__ cpair pmul(cpair p, uint32_t z) {
    const __half2 zv = *reinterpret_cast<const __half2*>(&z), pr = *reinterpret_cast<const __half2*>(&p.r), pi = *reinterpret_cast<const __half2*>(&p.i);
    const __half2 zr = __low2half2(zv), zi = __high2half2(zv);
    const __half2 a = __hfma2(__hneg2(pi), zi, __hmul2(pr, zr)), b = __hfma2(pi, zr, __hmul2(pr, zi));
    return {*reinterpret_cast<const uint32_t*>(&a), *reinterpret_cast<const uint32_t*>(&b)};
}
__device__ __forceinline__ uint32_t packz(cplx z) { return pack2h(z.r, z.i); }
__device__ __forceinline__ void wgmma_kg(float (&d)[24], uint64_t da, uint64_t db, int scale_d) {
    asm volatile("{\n.reg .pred p;\nsetp.ne.b32 p, %26, 0;\n"
                 "wgmma.mma_async.sync.aligned.m64n48k16.f32.f16.f16 "
                 "{%0,%1,%2,%3,%4,%5,%6,%7,%8,%9,%10,%11,%12,%13,%14,%15,%16,%17,%18,%19,%20,%21,%22,%23}, %24, %25, p, 1, 1, 1, 1;\n}\n"
                 : "+f"(d[0]), "+f"(d[1]), "+f"(d[2]), "+f"(d[3]), "+f"(d[4]), "+f"(d[5]), "+f"(d[6]), "+f"(d[7]), "+f"(d[8]), "+f"(d[9]),
                   "+f"(d[10]), "+f"(d[11]), "+f"(d[12]), "+f"(d[13]), "+f"(d[14]), "+f"(d[15]), "+f"(d[16]), "+f"(d[17]), "+f"(d[18]), "+f"(d[19]),
                   "+f"(d[20]), "+f"(d[21]), "+f"(d[22]), "+f"(d[23])
                 : "l"(da), "l"(db), "r"(scale_d));
}

struct SsmParams { const bf16 *lar, *aim, *cre, *cim, *logdt, *dskip; const unsigned* epoch; };
constexpr int KG_TABLES = 6 * 16384, KG_RES = 1664;
struct KgShared { uint32_t kmax[6], kexp[6]; float cinv[6], tap0[6]; };
struct KgParams { uint32_t l[3], a[3], r[3], i[3], dt, ds; };

__device__ __forceinline__ bool kg_is_hi(int warp) { return ((warp >> 1) ^ (warp >> 2)) & 1; }
__device__ __forceinline__ void kgen_load(KgParams& kp, int d0, int warp, int lane, const SsmParams& sp) {
    const int d = d0 + min(2 * (warp >> 2) + (warp & 1), 4), idx = d * (NMODE / 2) + lane;
    const bf16 *pr = kg_is_hi(warp) ? sp.cre : sp.lar, *pi = kg_is_hi(warp) ? sp.cim : sp.aim;
    kp.dt = __ldg((const uint16_t*)sp.logdt + d);
#pragma unroll
    for (int j = 0; j < 3; j++) {
        kp.l[j] = __ldg((const uint32_t*)sp.lar + idx + 32 * j); kp.a[j] = __ldg((const uint32_t*)sp.aim + idx + 32 * j);
        kp.r[j] = __ldg((const uint32_t*)pr + idx + 32 * j); kp.i[j] = __ldg((const uint32_t*)pi + idx + 32 * j);
    }
    kp.ds = __ldg((const uint16_t*)sp.dskip + d0 + min(warp >> 1, 4));
}

struct KgAnchors { uint32_t v[8]; };
__device__ __forceinline__ KgAnchors kg_anchor_lo(const KgParams& kp, uint32_t sel, float dt) {
    auto B = [&](uint32_t v) { return __uint_as_float(__byte_perm(v, 0u, sel)); };
    const float arl = -rbf(ex2(B(kp.l[0]) * 1.4426950408889634f)) * dt * 1.4426950408889634f, ai = B(kp.a[0]) * dt;
    const cplx z8 = cexp_p(arl, ai, 8.f), z16 = csq(z8), z24 = cmul(z16, z8), z32 = csq(z16), z64 = csq(z32), z128 = csq(z64), z192 = cmul(z128, z64);
    return {{pack2h(1.f, z8.r), pack2h(0.f, z8.i), pack2h(z16.r, z24.r), pack2h(z16.i, z24.i), packz(z32), packz(z64), packz(z128), packz(z192)}};
}
__device__ __forceinline__ KgAnchors kg_anchor_hi(const KgParams& kp, uint32_t sel, float dt, float cs) {
    auto B = [&](uint32_t v) { return __uint_as_float(__byte_perm(v, 0u, sel)); };
    const float arl = -rbf(ex2(B(kp.l[0]) * 1.4426950408889634f)) * dt * 1.4426950408889634f, ai = B(kp.a[0]) * dt;
    const cplx z1 = cexp_p(arl, -ai, 1.f), z2 = csq(z1), z4 = csq(z2), z256 = cexp_p(arl, -ai, 256.f), z512 = csq(z256), z1024 = csq(z512);
    const cplx H0 = {B(kp.r[0]) * cs, -B(kp.i[0]) * cs}, H4 = cmul(H0, z4);
    return {{pack2h(H0.r, H4.r), pack2h(H0.i, H4.i), packz(z1), packz(z2), packz(z256), packz(z512), packz(z1024), 0u}};
}

template <class Idle>
__device__ __forceinline__ void kgen_tables(KgParams& kp, uint32_t scr, uint32_t dump, KgShared* ks, int warp, int lane, Idle idle TS_ARG) {
    const int wg = warp >> 2, half = warp & 1, sw = lane & 7;
    const bool hi = kg_is_hi(warp);
    TS(23);
    const float dt = rbf(ex2(bf_lo(kp.dt) * 1.4426950408889634f));
    uint32_t sel = (wg == 2 && half) ? 0x3244u : 0x1044u;
    float cs = 0.f;
    KgAnchors an;
    if (hi) {
        uint32_t m = 0;
#pragma unroll
        for (int j = 0; j < 3; j++) m = __vmaxu2(m, __vmaxu2(kp.r[j] & 0x7FFF7FFFu, kp.i[j] & 0x7FFF7FFFu));
        m = __reduce_max_sync(~0u, max(m << 16, m & 0xFFFF0000u));
        const uint32_t e = min(max(__float_as_uint(2.f * dt * __uint_as_float(m)) >> 23, 2u), 252u);
        cs = 2.f * dt * __uint_as_float((253u - e) << 23);
        if (lane == 0) { ks->cinv[2 * wg + half] = __uint_as_float((e + 1u) << 23); ks->kmax[2 * wg + half] = 0u; }
        an = kg_anchor_hi(kp, sel, dt, cs);
    } else {
        an = kg_anchor_lo(kp, sel, dt);
    }
    float acc[24];
#pragma unroll
    for (int i = 0; i < 24; i++) acc[i] = 0.f;
    uint32_t tb = scr + 2 * wg * 16384 + lane * 128;
    uint64_t da = mkdesc(scr + 2 * wg * 16384, 4096, 1024, 1);
    int flip = 16384;
#pragma unroll 1
    for (int c = wg == 2 ? 1 : 0, step = wg == 2 ? 2 : 1; c < 6; c += step) {
        if (wg < 2) sel ^= 0x2200u;
        if (!hi) {
            if (c & 1) { kp.l[0] = kp.l[1]; kp.l[1] = kp.l[2]; kp.a[0] = kp.a[1]; kp.a[1] = kp.a[2]; }
            cpair p[4];
            p[0] = {an.v[0], an.v[1]}; p[1] = {an.v[2], an.v[3]};
            p[2] = pmul(p[0], an.v[4]); p[3] = pmul(p[1], an.v[4]);
#pragma unroll
            for (int j = 0; j < 4; j++) {
                cpair v[4];
#pragma unroll
                for (int i = 0; i < 4; i++) v[i] = j ? pmul(p[i], an.v[4 + j]) : p[i];
                const uint32_t a = tb + (((4 * half + j) ^ sw) << 4);
                sts128(a, make_uint4(v[0].r, v[1].r, v[2].r, v[3].r));
                sts128(a + 4096, make_uint4(v[0].i, v[1].i, v[2].i, v[3].i));
            }
            an = kg_anchor_lo(kp, sel, dt);
        } else {
            if (c & 1) {
#pragma unroll
                for (int j = 0; j < 2; j++) { kp.l[j] = kp.l[j + 1]; kp.a[j] = kp.a[j + 1]; kp.r[j] = kp.r[j + 1]; kp.i[j] = kp.i[j + 1]; }
            }
            const uint32_t h1 = an.v[2], h2 = an.v[3], h256 = an.v[4], h512 = an.v[5], h1024 = an.v[6];
            cpair p[11];
            p[0] = {an.v[0], an.v[1]};
            p[1] = pmul(p[0], h2); p[2] = pmul(p[0], h1); p[3] = pmul(p[1], h1);
            p[4] = pmul(p[0], h256); p[5] = pmul(p[1], h256); p[6] = pmul(p[0], h512); p[7] = pmul(p[4], h512);
            p[8] = pmul({__byte_perm(p[0].r, p[4].r, 0x5410), __byte_perm(p[0].i, p[4].i, 0x5410)}, h1024);
            p[9] = pmul(p[8], h512); p[10] = pmul(p[8], h1024);
#pragma unroll
            for (int j = 0; j < 3; j++) {
                const uint32_t a = tb + 8192 + (((3 * half + j) ^ sw) << 4);
                sts128(a, make_uint4(p[4 * j].r, p[4 * j + 1].r, p[4 * j + 2].r, p[j < 2 ? 4 * j + 3 : 10].r));
                sts128(a + 4096, make_uint4(p[4 * j].i, p[4 * j + 1].i, p[4 * j + 2].i, p[j < 2 ? 4 * j + 3 : 10].i));
            }
            an = kg_anchor_hi(kp, sel, dt, cs);
        }
        if (c == 0) TS(24);
        if (c == 3) TS(25);
        fence_async_smem();
        wg_wait<0>();
        named_bar(5 + wg, 128);
        wg_fence();
#pragma unroll
        for (int k = 0; k < 4; k++) wgmma_kg(acc, da + k * 128, da + 512 + k * 128, 1);
        wg_commit();
        tb += flip; da += flip >> 4; flip = -flip;
    }
    const bool up = warp & 2;
    const int r = 2 * wg + up, lo0 = 16 * half + (lane >> 2);
    const uint32_t o = dump + r * KG_RES + lo0 * 52 + 4 * (lane & 3);
    const float ci = __uint_as_float(lds32(s2u(&ks->cinv[r])));
    const float ds = warp <= 8 ? bf_lo(kp.ds) : 0.f;
    TS(26);
    idle();
    wg_wait<0>();
    float v[12], m = 0.f;
#pragma unroll
    for (int j = 0; j < 12; j++) { v[j] = up ? acc[12 + j] : acc[j]; m = fmaxf(m, fabsf(v[j])); }
#pragma unroll
    for (int j = 0; j < 6; j++) sts32(o + (j & 1) * 416 + (j >> 1) * 16, pack2h(v[2 * j], v[2 * j + 1]));
    const uint32_t mm = __reduce_max_sync(~0u, __float_as_uint(m));
    if (lane == 0) {
        asm volatile("red.shared.max.u32 [%0], %1;" ::"r"(s2u(&ks->kmax[r])), "r"(mm) : "memory");
        if (!half) ks->tap0[r] = fmaf(ci, v[0], ds);
    }
}
#define F_PPOS 0
#define F_STAG 4
__device__ __forceinline__ void wgmma_h64_rs(uint32_t (&d)[16], const uint4& a, uint64_t db, int scale_d) {
    asm volatile("{\n.reg .pred p;\nsetp.ne.b32 p, %21, 0;\n"
                 "wgmma.mma_async.sync.aligned.m64n64k16.f16.f16.f16 {%0,%1,%2,%3,%4,%5,%6,%7,%8,%9,%10,%11,%12,%13,%14,%15}, {%16,%17,%18,%19}, %20, p, 1, 1, 1;\n}\n"
                 : "+r"(d[0]), "+r"(d[1]), "+r"(d[2]), "+r"(d[3]), "+r"(d[4]), "+r"(d[5]), "+r"(d[6]), "+r"(d[7]), "+r"(d[8]), "+r"(d[9]),
                   "+r"(d[10]), "+r"(d[11]), "+r"(d[12]), "+r"(d[13]), "+r"(d[14]), "+r"(d[15])
                 : "r"(a.x), "r"(a.y), "r"(a.z), "r"(a.w), "l"(db), "r"(scale_d));
}
template <int TB>
__device__ __forceinline__ void wgmma_h32_rs(uint32_t (&d)[8], const uint4& a, uint64_t db, int scale_d) {
    asm volatile("{\n.reg .pred p;\nsetp.ne.b32 p, %13, 0;\n"
                 "wgmma.mma_async.sync.aligned.m64n32k16.f16.f16.f16 {%0,%1,%2,%3,%4,%5,%6,%7}, {%8,%9,%10,%11}, %12, p, 1, 1, %14;\n}\n"
                 : "+r"(d[0]), "+r"(d[1]), "+r"(d[2]), "+r"(d[3]), "+r"(d[4]), "+r"(d[5]), "+r"(d[6]), "+r"(d[7])
                 : "r"(a.x), "r"(a.y), "r"(a.z), "r"(a.w), "l"(db), "r"(scale_d), "n"(TB));
}
__device__ __forceinline__ void wgmma_s1(uint32_t (&d)[16], const uint4& a, uint64_t db, int scale_d) { wgmma_h64_rs(d, a, db, scale_d); }
__device__ __forceinline__ void wgmma_s1(uint32_t (&d)[8], const uint4& a, uint64_t db, int scale_d) { wgmma_h32_rs<1>(d, a, db, scale_d); }
__device__ __forceinline__ void wgmma_s4(float (&d)[32], const uint4& a, uint64_t db, uint32_t meta, int scale_d) {
    asm volatile("{\n.reg .pred p;\nsetp.ne.b32 p, %38, 0;\n"
                 "wgmma.mma_async.sp.sync.aligned.m64n64k32.f32.f16.f16 {%0,%1,%2,%3,%4,%5,%6,%7,%8,%9,%10,%11,%12,%13,%14,%15,%16,%17,%18,%19,%20,%21,%22,%23,%24,%25,%26,%27,%28,%29,%30,%31}, {%32,%33,%34,%35}, %36, %37, 0, p, 1, 1, 1;\n}\n"
                 : "+f"(d[0]), "+f"(d[1]), "+f"(d[2]), "+f"(d[3]), "+f"(d[4]), "+f"(d[5]), "+f"(d[6]), "+f"(d[7]), "+f"(d[8]), "+f"(d[9]), "+f"(d[10]), "+f"(d[11]), "+f"(d[12]), "+f"(d[13]), "+f"(d[14]), "+f"(d[15]), "+f"(d[16]), "+f"(d[17]), "+f"(d[18]), "+f"(d[19]), "+f"(d[20]), "+f"(d[21]), "+f"(d[22]), "+f"(d[23]), "+f"(d[24]), "+f"(d[25]), "+f"(d[26]), "+f"(d[27]), "+f"(d[28]), "+f"(d[29]), "+f"(d[30]), "+f"(d[31])
                 : "r"(a.x), "r"(a.y), "r"(a.z), "r"(a.w), "l"(db), "r"(meta), "r"(scale_d));
}
__device__ __forceinline__ void wgmma_s4(float (&d)[16], const uint4& a, uint64_t db, uint32_t meta, int scale_d) {
    asm volatile("{\n.reg .pred p;\nsetp.ne.b32 p, %22, 0;\n"
                 "wgmma.mma_async.sp.sync.aligned.m64n32k32.f32.f16.f16 {%0,%1,%2,%3,%4,%5,%6,%7,%8,%9,%10,%11,%12,%13,%14,%15}, {%16,%17,%18,%19}, %20, %21, 0, p, 1, 1, 1;\n}\n"
                 : "+f"(d[0]), "+f"(d[1]), "+f"(d[2]), "+f"(d[3]), "+f"(d[4]), "+f"(d[5]), "+f"(d[6]), "+f"(d[7]), "+f"(d[8]), "+f"(d[9]), "+f"(d[10]), "+f"(d[11]), "+f"(d[12]), "+f"(d[13]), "+f"(d[14]), "+f"(d[15])
                 : "r"(a.x), "r"(a.y), "r"(a.z), "r"(a.w), "l"(db), "r"(meta), "r"(scale_d));
}

__device__ __forceinline__ uint32_t& u4r(uint4& v, int i) { return i == 0 ? v.x : i == 1 ? v.y : i == 2 ? v.z : v.w; }

template <int NC>
__device__ __forceinline__ void fft_stage(const uint32_t (&u)[2][4], int c, uint32_t eo, int w, int lane) {
    const int mi = lane >> 3, mj = lane & 7;
    const uint32_t a = eo + (8 * w + mj) * 128 + (((4 * c + mi) ^ mj) << 4);
    stsm_x4(a, hadd(u[0][0], u[1][0]), hadd(u[0][1], u[1][1]), hadd(u[0][2], u[1][2]), hadd(u[0][3], u[1][3]));
    stsm_x4(NC == 2 ? a + 4096 : a ^ 64, hsub(u[0][0], u[1][0]), hsub(u[0][1], u[1][1]), hsub(u[0][2], u[1][2]), hsub(u[0][3], u[1][3]));
}
template <int NC>
__device__ __forceinline__ void kernel_stage(const uint4 (&ko)[2], uint32_t kt, KgShared* ks, int r, uint32_t eo, int w, int lane) {
    uint32_t u[2][2][4], sc[NC], t0[NC];
#pragma unroll
    for (int c = 0; c < NC; c++) {
        const float ci = ks->cinv[r + c], k0 = ks->tap0[r + c] + (NC == 1 ? ks->tap0[r + 1] : 0.f);
        const float mx = fmaxf(ci * (__uint_as_float(ks->kmax[r + c]) + (NC == 1 ? __uint_as_float(ks->kmax[r + 1]) : 0.f) + 0x1p-14f), fabsf(k0));
        const uint32_t e = min(max(__float_as_uint(mx) >> 23, 4u), 250u);
        const float s = __uint_as_float((253u - e) << 23), f = s * ci;
        if (w == 0 && lane == 0) ks->kexp[r + c] = e;
        sc[c] = pack2h(f, f); t0[c] = pack2h(k0 * s, 0.f);
    }
#pragma unroll
    for (int h = 0; h < 2; h++)
#pragma unroll
        for (int j = 0; j < 4; j++) {
            const uint32_t a0 = kt + (u4(ko[h], j) & 0xFFFF), a1 = kt + (u4(ko[h], j) >> 16);
#pragma unroll
            for (int c = 0; c < 2; c++)
                asm volatile("{\n.reg .b16 a, b;\nld.shared.b16 a, [%1];\nld.shared.b16 b, [%2];\nmov.b32 %0, {a, b};\n}"
                             : "=r"(u[c][h][j]) : "r"(a0 + c * KG_RES), "r"(a1 + c * KG_RES) : "memory");
            if (NC == 1) u[0][h][j] = hadd(u[0][h][j], u[1][h][j]);
#pragma unroll
            for (int c = 0; c < NC; c++) {
                u[c][h][j] = hmul(u[c][h][j], sc[c]);
                if (h + j == 0 && w == 0 && lane == 0) u[c][0][0] = __byte_perm(t0[c], u[c][0][0], 0x7610);
            }
        }
#pragma unroll
    for (int c = 0; c < NC; c++) fft_stage<NC>(u[c], c, eo, w, lane);
}

template <int NC, bool SHEAR, class Mid>
__device__ __forceinline__ void fft_forward(const uint4 (&a1)[4], const uint4 (&tw)[4], uint32_t eo, uint32_t s2, uint32_t (&X)[NC][2][8], Mid mid) {
    uint32_t dr[8 * NC], di[8 * NC];
    const uint64_t de = mkdesc(eo, 4096, 1024, 1), d2 = mkdesc(s2, 16, 1024, 1);
    wg_fence();
    wgmma_s1(dr, a1[0], de, 0);
    wgmma_s1(di, a1[2], de + (NC == 2 ? 256 : 4), 0);
    wgmma_s1(dr, a1[1], de + 128, 1);
    wgmma_s1(di, a1[3], de + (NC == 2 ? 384 : 132), 1);
    wg_commit();
    mid();
    wg_wait<0>();
#pragma unroll
    for (int c = 0; c < NC; c++) {
        uint4 zr[2], zi[2];
#pragma unroll
        for (int p = 0; p < 2; p++)
#pragma unroll
            for (int i = 0; i < 4; i++) {
                const uint32_t r = dr[8 * c + 4 * p + i], m = di[8 * c + 4 * p + i], tr = u4(tw[p], i), ti = u4(tw[2 + p], i);
                if (SHEAR) {
                    const uint32_t r1 = hfma(tr, m, r), m1 = hfma(ti, r1, m);
                    u4r(zr[p], i) = hfma(tr, m1, r1); u4r(zi[p], i) = m1;
                } else {
                    u4r(zr[p], i) = hfms(m, ti, hmul(r, tr));
                    u4r(zi[p], i) = hfma(m, tr, hmul(r, ti));
                }
            }
        wg_fence();
        wgmma_h32_rs<0>(X[c][0], zi[0], d2 + 2, 0);
        wgmma_h32_rs<0>(X[c][1], zi[1], d2 + 6, 0);
        wgmma_h32_rs<0>(X[c][0], zr[0], d2, 1);
        wgmma_h32_rs<0>(X[c][1], zr[1], d2 + 4, 1);
        wg_commit();
    }
}

template <int NC, class Idle, class Ready, class Staged>
__device__ __forceinline__ void conv_wg(int ch0, int layer, uint32_t eo, uint32_t zb, uint32_t s23, uint32_t kexp, uint32_t epoch, uint32_t st, uint32_t sbar,
                                        int warp, int lane, uint4 (&a1)[4], uint4 (&tw)[4], Idle idle, Ready ready, Staged staged TS_ARG) {
    const int wg = warp >> 2, w = warp & 3, t = 32 * w + lane, g = lane >> 2, q = lane & 3, mi = lane >> 3, mj = lane & 7;
    auto F = [](uint32_t x) { return __uint_as_float(x); };
    uint32_t KH[NC][2][8];
    TS(2);
    fft_forward<NC, false>(a1, tw, eo, s23, KH, [] {});
    named_bar(1 + wg, 128);
    uint4 a4[4];
#pragma unroll
    for (int i = 0; i < 4; i++) { tw[i] = ldg_tab(4 + i, t); if (NC == 2) a4[i] = ldg_tab(12 + i, t); }
    wg_wait<0>();
    TS(4);
    idle();
    uint2 x[NC][2][2];
    const int ra[2] = {16 * (8 * w + g) + 4 * q, 16 * (63 - 8 * w - g) + 4 * q};
    if (NC == 1) {
        uint4 s[8];
        TS(1);
#pragma unroll
        for (int i = 0; i < 8; i++) s[i] = make_uint4(layer, 0, 0, 0);
        int spin = 0;
        uint32_t bad;
        do {
            bad = 0;
#pragma unroll
            for (int i = 0; i < 8; i++)
                if (((s[i].x ^ layer) & 1u) == 0) s[i] = ld_ll4((const uint4*)(g_fs[i & 1] + 1024 * ((i >> 1) & 1) + ra[i >> 2]));
#pragma unroll
            for (int i = 0; i < 8; i++) bad |= ~(s[i].x ^ layer);
        } while ((bad & 1u) && ++spin < (1 << 18));
#pragma unroll
        for (int i = 0; i < 8; i++) sts128(st + i * 2048 + t * 16, s[i]);
        __syncwarp();
        if (lane == 0) mbar_arrive(sbar + 8 * w);
#pragma unroll
        for (int i = 0; i < 4; i++) a4[i] = ldg_tab(12 + i, t);
        TS(14);
    }
    ready();
    TS(5);
    auto xload = [&](int i) {
        const unsigned long long v = ld_ll((const unsigned long long*)(g_x1T + (size_t)(ch0 + (i >> 2)) * XP + 1024 * (i & 1) + ra[(i >> 1) & 1]));
        x[i >> 2][(i >> 1) & 1][i & 1] = make_uint2((uint32_t)v, (uint32_t)(v >> 32));
    };
#pragma unroll
    for (int i = 0; i < 4 * NC; i++) xload(i);
    if (F_PPOS == 0) staged();
    TS(6);
    for (int spin = 0; spin < (1 << 18); spin++) {
        uint32_t bad = 0;
#pragma unroll
        for (int i = 0; i < 4 * NC; i++) bad |= ~(x[i >> 2][(i >> 1) & 1][i & 1].x ^ layer);
        if (!(bad & 1u)) break;
#pragma unroll
        for (int i = 0; i < 4 * NC; i++) if (((x[i >> 2][(i >> 1) & 1][i & 1].x ^ layer) & 1u) == 0) xload(i);
    }
    __syncwarp();
    TS(26);
    if (NC == 2) mbar_wait(sbar + 8 * w, 0);
    {
        uint4 s[2][2][2];
        uint32_t u[NC][2][4];
#pragma unroll
        for (int h = 0; h < 2; h++) {
            if (NC == 1 || h == 0) {
#pragma unroll
                for (int i = 4 * h; i < (NC == 1 ? 4 * h + 4 : 8); i++) s[i >> 2][(i >> 1) & 1][i & 1] = lds128(st + i * 2048 + t * 16);
            }
            if (h == 0) TS(7);
#pragma unroll
            for (int c = 0; c < NC; c++)
#pragma unroll
                for (int j = 0; j < 4; j++) {
                    const uint4 &a = s[h][j >> 1][0], &b = s[h][j >> 1][1];
                    const uint32_t xv = (j & 1) ? x[c][h][j >> 1].y : x[c][h][j >> 1].x;
                    u[c][h][j] = pack2h(fmaf(bf_lo(xv), F(u4(a, 2 * (j & 1))), F(u4(b, 2 * (j & 1)))), fmaf(bf_hi(xv), F(u4(a, 2 * (j & 1) + 1)), F(u4(b, 2 * (j & 1) + 1))));
                }
        }
#pragma unroll
        for (int c = 0; c < NC; c++) fft_stage<NC>(u[c], c, eo, w, lane);
    }
    TS(8);
    fence_async_smem();
    TS(9);
    if (F_PPOS == 1) staged();
    named_bar(1 + wg, 128);
    uint32_t X[NC][2][8], Y[NC][2][8];
    uint32_t oscale[NC];
    fft_forward<NC, true>(a1, tw, eo, s23, X, [&] {
#pragma unroll
        for (int c = 0; c < NC; c++) oscale[c] = (lds32(kexp + 4 * c) + 3u) * 0x00800080u;
        if (layer) {
#pragma unroll
            for (int i = 0; i < 4 * NC; i++) asm volatile("mov.b32 %0, 0;\nmov.b32 %1, 0;" : "=r"(x[i >> 2][(i >> 1) & 1][i & 1].x), "=r"(x[i >> 2][(i >> 1) & 1][i & 1].y));
        }
        TS(3); if (F_PPOS == 2) staged(); if (F_STAG >= 2 && NC == 2 && wg == 1) named_bar(10 + w, 64); });
    if (F_STAG == 2 && NC == 2 && wg == 0) asm volatile("bar.arrive %0, 64;" ::"r"(10 + w) : "memory");
    TS(10);
    const uint64_t d3 = mkdesc(s23 + 4096, 16, 1024, 1);
#pragma unroll
    for (int c = 0; c < NC; c++) {
        wg_wait<NC - 1>();
        TS(11 + c);
        uint4 pr[2], pi[2];
#pragma unroll
        for (int i = 0; i < 4; i++) {
            const uint32_t er = X[c][0][i], ei = X[c][0][4 + i], orr = X[c][1][i], oi = X[c][1][4 + i];
            const uint32_t ar = KH[c][0][i], ai = KH[c][0][4 + i], br = KH[c][1][i], bi = KH[c][1][4 + i];
            u4r(pr[0], i) = hfms(bi, oi, hfma(br, orr, hfms(ai, ei, hmul(ar, er))));
            u4r(pi[0], i) = hfma(bi, orr, hfma(br, oi, hfma(ai, er, hmul(ar, ei))));
            u4r(pr[1], i) = hfms(ai, oi, hfma(ar, orr, hfms(bi, ei, hmul(br, er))));
            u4r(pi[1], i) = hfma(ai, orr, hfma(ar, oi, hfma(bi, er, hmul(br, ei))));
        }
        if (F_STAG == 3 + c && NC == 2 && wg == 0) asm volatile("bar.arrive %0, 64;" ::"r"(10 + w), "r"(pr[0].x ^ pr[1].w ^ pi[0].y ^ pi[1].z) : "memory");
        wg_fence();
        wgmma_h32_rs<0>(Y[c][0], pr[0], d3, 0);
        wgmma_h32_rs<0>(Y[c][1], pr[1], d3 + 4, 0);
        wgmma_h32_rs<0>(Y[c][0], pi[0], d3 + 2, 1);
        wgmma_h32_rs<0>(Y[c][1], pi[1], d3 + 6, 1);
        wg_commit();
    }
#pragma unroll
    for (int c = 0; c < NC; c++) {
        if (c + 1 < NC) wg_wait<1>(); else wg_wait<0>();
        TS(13 + c);
        uint32_t zr[2][4], zi[2][4];
#pragma unroll
        for (int p = 0; p < 2; p++)
#pragma unroll
            for (int i = 0; i < 4; i++) {
                const uint32_t r = Y[c][p][i], m = Y[c][p][4 + i], tr = u4(tw[p], i), ti = u4(tw[2 + p], i);
                const uint32_t r1 = hfms(tr, m, r), m1 = hfms(ti, r1, m);
                zr[i & 1][2 * p + (i >> 1)] = hfms(tr, m1, r1);
                zi[i & 1][2 * p + (i >> 1)] = m1;
            }
        const int kr = 4 * (mj >> 1) + (mj & 1) + 2 * (mj >> 2), ki = kr ^ 2;
#pragma unroll
        for (int h = 0; h < 2; h++) {
            const uint32_t a = zb + (2 * w + h) * 2048;
            stsm_x4(a + ki * 128 + (((4 * c + mi) ^ (ki & 7)) << 4), zi[h][0], zi[h][1], zi[h][2], zi[h][3]);
            stsm_x4(a + kr * 128 + (((4 * c + mi) ^ (kr & 7)) << 4), zr[h][0], zr[h][1], zr[h][2], zr[h][3]);
        }
    }
    TS(15);
    fence_async_smem();
    TS(16);
    named_bar(1 + wg, 128);
    TS(17);
    float acc[16 * NC];
    const uint64_t dz = mkdesc(zb, 4096, 1024, 1);
    wg_fence();
#pragma unroll
    for (int ks = 0; ks < 4; ks++) wgmma_s4(acc, a4[ks], dz + ks * 256, 0x44EEEE44u, ks > 0);
    wg_commit();
    uint32_t fb = ~lds32(epoch) & layer;
    const char* dst[2];
#pragma unroll
    for (int h = 0; h < 2; h++) {
        dst[h] = layer ? (const char*)&g_of[ch0 / 80][ra[h] >> 6][(ch0 % 80) * 16 + ((ra[h] >> 2) & 15)] : (const char*)(g_x2T + (size_t)ch0 * XP + ra[h]);
        asm volatile("mov.b64 %0, %0;" : "+l"(dst[h]));
    }
    wg_wait<0>();
    TS(18);
#pragma unroll
    for (int c = 0; c < NC; c++) {
        uint32_t r[2][4];
#pragma unroll
        for (int j = 0; j < 4; j++) {
            const float* d = acc + 4 * (4 * c + j);
            const uint32_t y0 = pack2(d[0] + d[2], d[1] + d[3]), y1 = pack2(d[0] - d[2], d[1] - d[3]);
            asm("fma.rn.bf16x2 %0, %1, %2, %3;" : "=r"(r[0][j]) : "r"(y0), "r"(oscale[c]), "r"((j & 1) ? x[c][0][j >> 1].y : x[c][0][j >> 1].x));
            asm("fma.rn.bf16x2 %0, %1, %2, %3;" : "=r"(r[1][j]) : "r"(y1), "r"(oscale[c]), "r"((j & 1) ? x[c][1][j >> 1].y : x[c][1][j >> 1].x));
        }
#pragma unroll
        for (int h = 0; h < 2; h++)
            asm volatile("{\n.reg .pred p;\n.reg .b128 t;\n.reg .b64 a, b;\nsetp.ne.u32 p, %5, 0;\nmov.b64 a, {%1, %2};\nmov.b64 b, {%3, %4};\nmov.b128 t, {a, b};\n"
                         "@p st.relaxed.gpu.global.b128 [%0], t;\n@!p st.global.b64 [%6], a;\n@!p st.global.b64 [%6 + 2048], b;\n}"
                         ::"l"(dst[h] + c * 256), "r"((r[h][0] & ~layer) | fb), "r"(r[h][1]), "r"(r[h][2]), "r"(r[h][3]), "r"(layer), "l"(dst[h] + c * XP * 2) : "memory");
    }
    TS(19);
}

#define Q_SCHED 3
#define Q_WAITFOR(it) (Q_SCHED == 0 ? (it) - 2 : Q_SCHED == 1 ? ((it) == 3 ? 1 : 0) : Q_SCHED == 2 ? -1 : (it) - 1)
#define Q_S0 8
#define A_HPOS 1
#define A_CSPRE 2
#define R_CONS 192
#define F_PRE 4
#define T_PF 1
#define K_CSUN 1
constexpr int K_CSU = K_CSUN;
#define G_MAP 1
#define O_TPOS 6
#define O_PASS 0
#define O_DEPTH 3
#define Q_SP 2
#define X_HINT 1
#define S_FIRST 1
#define A_VLO 4
constexpr int Q_ST = 4;
constexpr int Q_AB = 16384, Q_BB = 30720, Q_SB = Q_AB + Q_BB;
constexpr int Q_EROW = 336;
constexpr int Q_ESLOT = 8 * Q_EROW;
constexpr int Q_EOFF = Q_ST * Q_SB;
constexpr int Q_KG = 2 * Q_SB;
static_assert(3 * Q_ESLOT <= 8192 && Q_KG + KG_TABLES <= Q_EOFF + 4096, "exchange slots, kernel generation");
constexpr int F_EO = Q_EOFF, F_S23 = F_EO + 2 * 8192 + 4096, Q_KDUMP = F_S23 + 8192;
constexpr int Q_SMEM = Q_KDUMP + 6 * KG_RES + TS_SMEM;
__host__ __device__ constexpr int w_grp(int j) { return j < 7 ? 2 * Q_SB + j * 12800 : 0; }
constexpr int W_RES = Q_AB, W_OUT = Q_SB + Q_AB;

constexpr int Q_WOT = Q_EOFF + 4096;

__device__ unsigned g_epoch;
__device__ __align__(1024) unsigned g_bar[4][16][32];
__device__ __align__(1024) uint4 g_wop[8][80][10][8];
__device__ __align__(1024) uint4 g_csp[8][16][96];
__device__ __align__(1024) uint4 g_stp[16][8][64];
__device__ __align__(1024) uint4 g_sp2[16][8][8][8];
__device__ __align__(1024) uint4 g_halo[128][2][5][32];

struct Bars { uint64_t full[Q_ST], empty[Q_ST], wfull[3], ex[7], res, go, qdone, prep, ardy, hdone, fdone, idx, att1, pass, wfree, soon[2], st[4], kfree, staged; };
constexpr int NBAR = sizeof(Bars) / 8;
__host__ __device__ constexpr int bar_count(int i) {
#define BAR_IS(f) (i == offsetof(Bars, f) / 8)
    return (i >= 4 && i < 8) ? 16 : (BAR_IS(go) || (i >= offsetof(Bars, att1) / 8 && i < offsetof(Bars, st) / 8)) ? 4 : BAR_IS(qdone) ? 8 : BAR_IS(prep) ? 96 :
           BAR_IS(hdone) ? 6 : BAR_IS(fdone) ? 3 : BAR_IS(kfree) ? 24 : BAR_IS(staged) ? 2 : 1;
}
__device__ __forceinline__ void grid_wait(const unsigned* c, int n, unsigned target, int lane) {
    const unsigned* p = c + 32 * min(lane, n - 1);
    unsigned v;
    int spin = 0;
    do { asm volatile("ld.relaxed.gpu.global.u32 %0, [%1];" : "=r"(v) : "l"(p) : "memory"); } while (!__all_sync(~0u, (int)(v - target) >= 0) && ++spin < (1 << 18));
    fence_acquire();
}
__device__ __forceinline__ void grid_arrive(unsigned* c) {
    fence_release();
    asm volatile("red.relaxed.gpu.global.add.u32 [%0], 1;" ::"l"(c) : "memory");
}

#define TMAP(n) ([] { const CUtensorMap* p_; asm volatile("{\n.reg .b64 t;\nmov.b64 t, fused_kernel_param_" #n ";\ncvta.param.u64 %0, t;\n}" : "=l"(p_)); return p_; }())
extern "C" __global__ void __launch_bounds__(384, 1)
fused_kernel(const SsmParams sp, const __grid_constant__ CUtensorMap mX0, const __grid_constant__ CUtensorMap mX1, const __grid_constant__ CUtensorMap mW,
             const __grid_constant__ CUtensorMap mWr,
             const __grid_constant__ CUtensorMap mRes0, const __grid_constant__ CUtensorMap mRes1, const __grid_constant__ CUtensorMap mOut,
             const __grid_constant__ CUtensorMap mWo, const __grid_constant__ CUtensorMap mFin, const __grid_constant__ CUtensorMap mResA) {
    extern __shared__ __align__(1024) char smraw[];
    __shared__ __align__(8) Bars s_bar[2];
    __shared__ __align__(16) float s_cs[240], s_mean[2][64], s_rstd[2][72];
    __shared__ KgShared s_kg;
    __shared__ uint32_t s_epoch;
    const uint32_t sb = s2u(smraw);
    int tid, warp, lane, bx, rank, blk, hg, rot, c0;
    int role;
    {
        const int c = blockIdx.x >> 1, d = c - 41, r = d >= 21 ? 3 : d >= 14 ? 2 : d >= 7 ? 1 : 0;
        const int gp = c < 4 ? 0 : c <= 40 ? (c + 7) & 7 : d - 7 * r + 1;
        const int k = c < 4 ? c : c <= 40 ? (c >> 3) + (gp == 0 ? 3 : gp >= 3 && gp < 7 ? 0 : -1) : (gp >= 3 ? 5 : 4) + r;
        role = G_MAP == 1 ? 16 * k + 2 * gp + (blockIdx.x & 1) : G_MAP == 2 ? 16 * gp + 2 * k + (blockIdx.x & 1) : blockIdx.x;
    }
    auto indices = [&] {
        asm volatile("mov.u32 %0, %%tid.x;" : "=r"(tid));
        asm volatile("mov.u32 %0, %1;" : "=r"(bx) : "r"(role));
        warp = __shfl_sync(~0u, tid >> 5, 0); lane = tid & 31;
        rank = bx & 1; blk = bx & 15; hg = bx >> 4;
        const int u = ((blk >> 1) + hg) & 7;
        rot = (5 * u) >> 2; c0 = 16 * (u & 3);
    };
    indices();
    TS_DECL;
    TS_BEGIN;
#define EPOCH lds32(s2u(&s_epoch))
    int layer = 0;
    uint32_t bars = s2u(s_bar);
#define BAR(f) (bars + (uint32_t)offsetof(Bars, f))
    auto chunk = [&](int it, int s0) {
        const int i = it < s0 ? it : it - 2;
        return (it >> 1) == (s0 >> 1) ? rot + (it & 1) : i < rot ? i : i + 2;
    };
    auto osrc_of = [&](int j) { return j == 0 ? hg : j - 1 < hg ? j - 1 : j; };
    auto issue_w = [&](uint32_t bb, int it, int lay) {
        const int half = rank;
        const int s = it & (Q_ST - 1);
        const uint32_t fb = bb + 8 * s, db = sb + s * Q_SB + Q_AB + half * 15360;
        const int k0 = chunk(it, Q_SP * lay) * 64 + half * 32;
#pragma unroll
        for (int p = 0; p < 3; p++) tma2d_mc(db + p * 4096, TMAP(3), p * DM + hg * 80, k0, fb, 3);
        tma3d_mc(db + 12288, TMAP(4), hg * 80 + 64, k0, 0, fb, 3);
    };
    auto issue_x = [&](int it) {
        const int s = it & (Q_ST - 1), kc = chunk(it, Q_SP * layer);
        mbar_expect(BAR(full) + 8 * s, Q_SB);
        tma3d(sb + s * Q_SB, TMAP(1) + layer, (layer ? blk : kc) * 64, (layer ? kc : blk) * 64, 0, BAR(full) + 8 * s);
    };
    {
        KgParams kp;
        const uint32_t epoch0 = ldg32(sp.epoch);
        kgen_load(kp, bx * 5, warp, lane, sp);
        if (warp < 8) {
            cluster_arrive_relaxed();
        } else {
            if (elect_one()) {
                if (warp < 10) { prefetch_tmap(TMAP(3)); prefetch_tmap(TMAP(4)); } else prefetch_tmap(warp == 10 ? TMAP(1) : TMAP(8));
                const uint32_t b0 = bars + (warp >= 10 ? sizeof(Bars) : 0);
                if (warp & 1) {
#pragma unroll
                    for (int i = 0; i < NBAR / 2; i++) mbar_init(b0 + i * 8, bar_count(i));
                } else {
#pragma unroll
                    for (int i = NBAR / 2; i < NBAR; i++) mbar_init(b0 + i * 8, bar_count(i));
                }
                fence_mbar_init();
            }
            __syncwarp();
            cluster_arrive_relaxed();
            TS(29);
            cluster_wait();
            TS(27);
            if (elect_one()) {
                if (warp < 10) {
                    issue_w(BAR(full), warp - 8, 0);
                } else if (warp == 10) {
                    issue_x(0); issue_x(1);
                    prefetch_l2((const char*)c_fft + bx * (sizeof(c_fft) / 128), sizeof(c_fft) / 128);
                } else {
                    mbar_expect(BAR(idx), 8192 + 6400);
                    asm volatile("cp.async.bulk.tensor.4d.shared::cluster.global.mbarrier::complete_tx::bytes [%0], [%1, {0, 0, %3, %4}], [%2];"
                                 ::"r"(sb + Q_WOT), "l"(TMAP(8)), "r"(BAR(idx)), "r"(10 * hg), "r"(5 * blk) : "memory");
                    bulk_g2s(sb + F_S23, c_fft + 18 * 512, 8192, BAR(idx));
                }
            }
            __syncwarp();
            TS(30);
        }
        indices();
        kgen_tables(kp, sb + Q_KG, sb + Q_KDUMP, &s_kg, warp, lane, [&] { if (warp < 8) cluster_wait(); } TS_PASS);
        __syncwarp();
        if (lane == 0) { mbar_arrive_cta(BAR(kfree), 0); mbar_arrive_cta(BAR(kfree), 1); }
        if (warp >= 8) {
            const int t2 = tid - 256;
            float csum[10];
            if (t2 == 0) s_epoch = epoch0;
            if (t2 < 64) stg128(&g_sp2[blk][hg][0][0] + t2, make_uint4(0, 0, 0, 0));
            if (t2 >= 120) stg128((uint4*)g_fs + 8 * bx + t2 - 120, make_uint4(0, 0, 0, 0));
            if (t2 < 64) stg128(g_x1T + (size_t)(5 * bx + 4) * XP + 64 * (t2 >> 1) + 48 + 8 * (t2 & 1), make_uint4(0, 0, 0, 0));
#pragma unroll
            for (int i = 0; i < 3; i++)
                if (t2 + 128 * i < 320) stg128(&g_halo[bx][0][0][0] + t2 + 128 * i, make_uint4(0, 0, 0, 0));
            if (warp == 8) asm volatile("bar.arrive 13, 128;" ::: "memory"); else named_bar(13, 128);
            if (warp > 8) {
                const int hw = warp - 9, mi = lane >> 3, mj = lane & 7;
                mbar_wait(BAR(idx), 0);
                if (hw == 2 && elect_one()) { bulk_s2g(&g_wop[hg][5 * blk], sb + Q_WOT, 6400); bulk_commit(); }
                __syncwarp();
                mbar_wait(BAR(full), 0);
                mbar_wait(BAR(full) + 8, 0);
#pragma unroll
                for (int f = 0; f < 10; f++) csum[f] = 0.f;
#pragma unroll K_CSU
                for (int G = 0; G < 5; G++) {
                    const int row = c0 + 40 * rank + 8 * G + mj;
                    const uint32_t b = sb + (row >> 6) * Q_SB + Q_AB + ((row >> 5) & 1) * 15360;
                    uint32_t r[10];
                    ldsm_x4_t(r[0], r[1], r[2], r[3], b + hw * 4096 + (row & 31) * 128 + ((mi ^ mj) << 4));
                    ldsm_x4_t(r[4], r[5], r[6], r[7], b + hw * 4096 + (row & 31) * 128 + (((4 + mi) ^ mj) << 4));
                    ldsm_x2_t(r[8], r[9], b + 12288 + hw * 1024 + (row & 31) * 32 + (((mi & 1) ^ (mj >> 2)) << 4));
#pragma unroll
                    for (int f = 0; f < 10; f++) csum[f] += bf_lo(r[f]) + bf_hi(r[f]);
                }
                const int q = lane & 3;
                float t[3];
#pragma unroll
                for (int j = 0; j < 3; j++) {
                    float v[4];
#pragma unroll
                    for (int k = 0; k < 4; k++) v[k] = 4 * j + k < 10 ? csum[4 * j + k] : 0.f;
                    const float a0 = ((q & 2) ? v[2] : v[0]) + __shfl_xor_sync(~0u, (q & 2) ? v[0] : v[2], 2);
                    const float a1 = ((q & 2) ? v[3] : v[1]) + __shfl_xor_sync(~0u, (q & 2) ? v[1] : v[3], 2);
                    t[j] = ((q & 1) ? a1 : a0) + __shfl_xor_sync(~0u, (q & 1) ? a0 : a1, 1);
                }
                st_ll4(&g_csp[hg][blk][tid - 288], ~EPOCH & 1u, __float_as_uint(t[0]), __float_as_uint(t[1]), __float_as_uint(t[2]));
            }
        }
        TS(1);
    }

    uint4 fa1[4], ftw[4];
    auto conv_tables = [&] {
#pragma unroll
        for (int i = 0; i < 4; i++) { fa1[i] = ldg_tab(i, tid & 127); ftw[i] = ldg_tab(8 + i, tid & 127); }
    };
    auto conv_done = [&] {
        if (layer == 0) {
            named_bar(1 + (warp >> 2), 128);
            if ((tid & 127) == 0) {
                mbar_arrive(BAR(fdone));
                grid_arrive(g_bar[2][hg]);
            }
            __syncwarp();
        }
        TS(20);
    };
    if (warp >= 8) {
    asm volatile("setmaxnreg.dec.sync.aligned.u32 %0;" ::"n"(504 - 2 * R_CONS));
#pragma unroll 1
    for (; layer < 2; layer++, bars += sizeof(Bars)) {
        indices();
        TS_PHASE(2 * layer);
        if (warp == 8) {
            if (layer) {
                grid_wait(g_bar[2][0], 8, 48 * (EPOCH + 1), lane);
                mbar_wait(BAR(fdone) - sizeof(Bars), 0);
                fence_async_global();
                TS(1);
            }
            if (elect_one()) {
#pragma unroll 1
                for (int it = layer ? 0 : 2; it < 10; it++) {
                    if (it >= Q_ST) mbar_wait(BAR(empty) + 8 * (it & (Q_ST - 1)), ((it >> 2) - 1) & 1);
                    else if (layer == 0) mbar_wait(BAR(kfree), 0);
                    else if (it > 0 && Q_WAITFOR(it) >= 0) mbar_wait(BAR(full) + 8 * Q_WAITFOR(it), 0);
                    if (it == Q_ST + Q_SP * layer) mbar_wait(BAR(hdone), 0);
                    issue_x(it);
                    if (layer == 0 || it >= F_PRE) issue_w(BAR(full), it, layer);
                }
                if (T_PF) { prefetch_tmap(TMAP(5) + layer); prefetch_tmap(TMAP(7)); prefetch_tmap(TMAP(10)); }
                if (layer == 0) { mbar_wait(BAR(prep), 0); fence_async_global(); }
#pragma unroll 1
                for (int j = 0; j < 8; j++) {
                    const int b = (j + 1) >> 2;
                    const uint32_t fb = BAR(wfull) + 8 * b;
                    if (j == 0 || j == 3 || j == 7) {
                        mbar_wait(BAR(empty) + 8 * ((2 + b) & 3), b < 2);
                        TS(11 + b);
                        mbar_expect(fb, (b == 0 ? 3 : b == 1 ? 4 : 1) * 12800);
                    }
                    bulk_g2s_mc(sb + w_grp(j) + rank * 6400, &g_wop[hg][osrc_of(j) * 10 + rank * 5], 6400, fb, 3);
                }
                mbar_expect(BAR(res), 20480);
                if (layer) {
                    tma3d(sb + W_RES, TMAP(6), blk * 64, hg * 80, 0, BAR(res));
                } else {
#pragma unroll 1
                    for (int p = 0; p < 2; p++) {
                        tma3d(sb + W_RES + p * 10240, TMAP(10), hg * 80, blk * 64, p, BAR(res));
                        tma3d(sb + W_RES + p * 10240 + 8192, TMAP(5), hg * 80 + 64, blk * 64, p, BAR(res));
                    }
                }
            }
            __syncwarp();
        } else {
            const int ht = tid - 288, hw = warp - 9, mi = lane >> 3, mj = lane & 7, g = lane >> 2, q = lane & 3;
            auto F = [](uint32_t x) { return __uint_as_float(x); };
            auto U = [](float x) { return __float_as_uint(x); };
            const uint32_t lb = layer ^ 1, eb = ~EPOCH & 1u;
            mbar_wait(BAR(full) + 8 * Q_SP * layer, 0);
            mbar_wait(BAR(full) + 8 * Q_SP * layer + 8, 0);
            if (ht == 0) TSX(2, 2);
            uint32_t xf[3][20];
#pragma unroll
            for (int i = 0; i < 3; i++) {
                const int tile = min(hw + 3 * i, 7);
#pragma unroll
                for (int k = 0; k < 5; k++) {
                    const int ch = c0 + 16 * k + 8 * (mi >> 1), tok = 16 * (tile & 3) + 8 * (mi & 1);
                    const uint32_t a = sb + ((ch >> 6) + Q_SP * layer) * Q_SB + (tile >> 2) * 8192;
                    if (layer == 0) ldsm_x4(xf[i][4 * k], xf[i][4 * k + 1], xf[i][4 * k + 2], xf[i][4 * k + 3], a + (tok + mj) * 128 + ((((ch & 63) >> 3) ^ mj) << 4));
                    else ldsm_x4_t(xf[i][4 * k], xf[i][4 * k + 1], xf[i][4 * k + 2], xf[i][4 * k + 3], a + ((ch & 63) + mj) * 128 + (((tok >> 3) ^ mj) << 4));
                }
            }
            fence_async_smem();
            __syncwarp();
            if (lane == 0) { mbar_arrive_cta(BAR(hdone), 0); mbar_arrive_cta(BAR(hdone), 1); }
            if (ht == 0) TSX(2, 3);
            if (layer == 0) {
                if (hw == 2 && elect_one()) { bulk_wait(); fence_async_global(); grid_arrive(g_bar[3][hg]); }
                __syncwarp();
                mbar_wait(BAR(kfree), 0);
            }
            if (ht == 0) TSX(2, 8);
#pragma unroll 1
            for (int tile = hw; tile < 8; tile += 3) {
                float a[4] = {0.f, 0.f, 0.f, 0.f};
#pragma unroll
                for (int j = 0; j < 20; j++) {
                    const float lo = bf_lo(xf[0][j]), hi = bf_hi(xf[0][j]);
                    a[2 * (j & 1)] += lo + hi; a[2 * (j & 1) + 1] = fmaf(lo, lo, fmaf(hi, hi, a[2 * (j & 1) + 1]));
                    xf[0][j] = xf[1][j]; xf[1][j] = xf[2][j];
                }
#pragma unroll
                for (int j = 0; j < 4; j++) { a[j] += __shfl_xor_sync(~0u, a[j], 1); a[j] += __shfl_xor_sync(~0u, a[j], 2); }
                if (q == 0) st_ll4(&g_stp[blk][hg][8 * tile + g], (U(a[0]) & ~1u) | lb, U(a[1]), U(a[2]), U(a[3]));
            }
            if (ht == 0) TSX(2, 4);
            if (layer == 0) {
                float t[4] = {0.f, 0.f, 0.f, 0.f};
                uint4 v[16];
                int spin = 0;
                uint32_t bad;
                do {
                    bad = 0;
#pragma unroll
                    for (int j = 0; j < 16; j++) v[j] = ld_ll4(&g_csp[hg][j][ht]);
#pragma unroll
                    for (int j = 0; j < 16; j++) bad |= v[j].x ^ eb;
                } while ((bad & 1u) && ++spin < (1 << 18));
#pragma unroll
                for (int j = 0; j < 16; j++) { t[0] += F(v[j].y); t[1] += F(v[j].z); t[2] += F(v[j].w); }
#pragma unroll
                for (int j = 0; j < 3; j++) if (q + 4 * j < 10) s_cs[80 * hw + 20 * (g >> 1) + 2 * (q + 4 * j) + (g & 1)] = t[j];
                if (hw == 2) grid_wait(g_bar[3][0], 8, 16 * (EPOCH + 1), lane);
            }
            if (ht == 0) TSX(2, 15);
            if (ht < 80) {
                const bool halo = ht >= 64;
                const int p = halo ? (ht >> 3) & 1 : ht >> 5, i = halo ? (ht & 7) - 8 : 8 + 2 * (ht & 24) + (ht & 7);
                const uint4* src = &g_stp[halo && blk ? blk - 1 : blk][0][halo ? 32 * p + 24 + (ht & 7) : ht];
                uint4 v[8];
                int spin = 0;
                uint32_t bad;
                do {
                    bad = 0;
#pragma unroll
                    for (int j = 0; j < 8; j++) v[j] = ld_ll4(src + 64 * j);
#pragma unroll
                    for (int j = 0; j < 8; j++) bad |= v[j].x ^ lb;
                } while ((bad & 1u) && ++spin < (1 << 18));
                float t[4] = {0.f, 0.f, 0.f, 0.f};
#pragma unroll
                for (int j = 0; j < 8; j++) { t[0] += F(v[j].x); t[1] += F(v[j].y); t[2] += F(v[j].z); t[3] += F(v[j].w); }
                const uint32_t s0 = ln_finish_packed(t[0], t[1]), s1 = ln_finish_packed(t[2], t[3]);
                if (!halo) { s_mean[p][i - 8] = bf_hi(s0); s_mean[p][i] = bf_hi(s1); s_rstd[p][i] = frcp(bf_lo(s0)); }
                s_rstd[p][i + 8] = frcp(bf_lo(s1));
            }
            fence_acquire();
            mbar_arrive(BAR(prep));
            if (ht == 0) TSX(2, 5);
        }
        __syncwarp();
        TS_PHASE(2 * layer + 1);
        TS(0);
        indices();
        {
            const uint4 ko[2] = {ldg_tab(16, tid & 127), ldg_tab(17, tid & 127)};
            conv_tables();
            mbar_wait(BAR(att1), 0);
            kernel_stage<1>(ko, sb + Q_KDUMP + 4 * KG_RES, &s_kg, 4, sb + F_EO + 2 * 8192, warp & 3, lane);
            fence_async_smem();
            named_bar(3, 128);
        }
        conv_wg<1>(5 * bx + 4, layer, sb + F_EO + 2 * 8192, sb + 2 * Q_SB, sb + F_S23, s2u(&s_kg.kexp[4]), s2u(&s_epoch), sb + 3 * Q_SB, BAR(st), warp, lane, fa1, ftw,
        [&] {
            if (warp == 9) {
                auto F = [](uint32_t x) { return __uint_as_float(x); };
                mbar_wait(BAR(soon) + 8 * (hg >> 2), 0);
                TS(23);
                const uint4* src = &g_sp2[blk][hg][0][0] + lane;
                uint4* dst = (uint4*)(g_fs[(lane >> 2) & 1] + 1024 * (hg >> 2) + 64 * blk + 16 * (hg & 3)) + (lane & 3);
                const bool up = lane & 8;
#pragma unroll 1
                for (int spin = 0; spin < (1 << 18); spin++) {
                    const uint4 a = ld_ll4(src), b = ld_ll4(src + 32);
                    const bool ok = !__any_sync(~0u, ~((a.x ^ layer) & (b.x ^ layer)) & 1u);
                    const float s0 = F(a.x) + F(b.x), q0 = F(a.y) + F(b.y), s1 = F(a.z) + F(b.z), q1 = F(a.w) + F(b.w);
                    float sm = (up ? s1 : s0) + __shfl_xor_sync(~0u, up ? s0 : s1, 8), sq = (up ? q1 : q0) + __shfl_xor_sync(~0u, up ? q0 : q1, 8);
                    sm += __shfl_xor_sync(~0u, sm, 16); sq += __shfl_xor_sync(~0u, sq, 16);
                    const float m = sm * (1.0f / DM), r = frsq(fmaxf(fmaf(sq, 1.0f / DM, fmaf(-m, m, 1e-5f)), 1e-5f));
                    const uint32_t v = __float_as_uint(lane & 16 ? -m * r : r);
                    const uint32_t v0 = __shfl_sync(~0u, v, 4 * lane), v1 = __shfl_sync(~0u, v, 4 * lane + 1), v2 = __shfl_sync(~0u, v, 4 * lane + 2), v3 = __shfl_sync(~0u, v, 4 * lane + 3);
                    if (ok && lane < 8) st_ll4(dst, (v0 & ~1u) | (layer ^ 1), v1, v2, v3);
                    if (ok) break;
                }
            }
            TS(25);
            mbar_wait(BAR(staged), 0);
        }, [&] { mbar_wait(BAR(ardy), 0); }, [&] {
            if (T_PF && tid == 352) prefetch_tmap(layer ? TMAP(9) : TMAP(2));
            if (layer == 0 && warp - 8 < F_PRE && elect_one()) { mbar_wait(BAR(wfree), 0); issue_w(BAR(full) + sizeof(Bars), warp - 8, 1); }
            __syncwarp();
        } TS_PASS);
        conv_done();
    }
    } else {
#pragma unroll 1
    for (; layer < 2; layer++, bars += sizeof(Bars)) {
    indices();
    TS_PHASE(2 * layer);
    const int wg = warp >> 2, w = warp & 3;
    const int mi = lane >> 3, mj = lane & 7, g = lane >> 2, q = lane & 3;
    TS(2);
    float acc[120];
#pragma unroll
    for (int i = 0; i < 120; i++) acc[i] = 0.f;
    auto release = [&](int it) {
        if (lane == 0) { mbar_arrive_cta(BAR(empty) + 8 * (it & (Q_ST - 1)), 0); mbar_arrive_cta(BAR(empty) + 8 * (it & (Q_ST - 1)), 1); }
    };
#pragma unroll 1
    for (int it = 0; it < 10; it++) {
        const int s = it & (Q_ST - 1);
        const uint32_t st = sb + s * Q_SB;
        const bool hold = wg == 1 && it == Q_S0;
        if (hold) {
            wg_wait<0>();
            release(it - 1);
            mbar_wait(BAR(go), 0);
        }
        mbar_wait(BAR(full) + 8 * (s), (it >> 2) & 1);
        if (it < 2) TS(3 + it);
        if (it == 6) TS(5);
        if (it == 9) TS(6);
        const uint64_t da = mkdesc(st + wg * 8192, 16, 1024, 1);
        const uint64_t db = mkdesc(st + Q_AB, 4096, 1024, 1);
        const uint64_t dr = mkdesc(st + Q_AB + 12288, 1024, 256, 3);
        if (layer == 0) {
            wg_fence();
#pragma unroll
            for (int ks = 0; ks < 4; ks++) {
                const int sc = 1;
                wgmma_n192<0, 1>(*(float(*)[96]) & acc[0], da + ks * 2, db + (ks >> 1) * 960 + (ks & 1) * 128, sc);
                wgmma_n48<0, 1>(*(float(*)[24]) & acc[96], da + ks * 2, dr + (ks >> 1) * 960 + (ks & 1) * 32, sc);
            }
            wg_commit();
        } else {
            wg_fence();
#pragma unroll
            for (int ks = 0; ks < 4; ks++) {
                const int sc = 1;
                wgmma_n192<1, 1>(*(float(*)[96]) & acc[0], da + ks * 128, db + (ks >> 1) * 960 + (ks & 1) * 128, sc);
                wgmma_n48<1, 1>(*(float(*)[24]) & acc[96], da + ks * 128, dr + (ks >> 1) * 960 + (ks & 1) * 32, sc);
            }
            wg_commit();
        }
        wg_wait<1>();
        if (it > 0 && !hold) release(it - 1);
    }
    if (wg == 0 && lane == 0) mbar_arrive(BAR(go));
    asm volatile("setmaxnreg.inc.sync.aligned.u32 %0;" ::"n"(R_CONS));
    mbar_wait(BAR(prep), 0);
    const uint32_t ob = layer ^ 1;
    const bool first = (blk == 0 && w == 0);
    const bool sel0 = (2 * q > g), sel1 = (2 * q + 1 > g);
    constexpr float SC = 0.22360679774997896f * 1.4426950408889634f;
    const float m0 = s_mean[wg][16 * w + g], m1 = s_mean[wg][8 + 16 * w + g];
    uint4 cs[3][5];
    auto cs_load = [&](int p) {
#pragma unroll
        for (int i = 0; i < 5; i++) cs[p][i] = lds128(s2u(&s_cs[80 * p + 20 * q + 4 * i]));
    };
    if (A_CSPRE >= 1) cs_load(1);
    if (A_CSPRE >= 2) cs_load(2);
    wg_wait<0>();
    if (A_CSPRE < 1) cs_load(1);
    if (A_CSPRE < 2) cs_load(2);
    TS(7);
    if (lane == 0) mbar_arrive(BAR(qdone));
    uint32_t ql[10], qh[10], kl[10], kh[10], vl[10], vh[10];
    auto fold = [&](int p, int f, int h) {
        const int j = (f < 8) ? 8 * p + f : 24 + 2 * p + (f - 8);
        const float c0 = __uint_as_float(u4(cs[p][f >> 1], 2 * (f & 1))), c1 = __uint_as_float(u4(cs[p][f >> 1], 2 * (f & 1) + 1));
        const float m = h ? m1 : m0;
        return pack2(fmaf(-m, c0, acc[4 * j + 2 * h]), fmaf(-m, c1, acc[4 * j + 2 * h + 1]));
    };
#pragma unroll
    for (int f = 0; f < 10; f++) { vh[f] = fold(2, f, 1); if (f < A_VLO) vl[f] = fold(2, f, 0); }
#pragma unroll
    for (int f = 0; f < 10; f++) kh[f] = fold(1, f, 1);
#pragma unroll
    for (int f = 0; f < A_VLO; f++) asm volatile("" : "+r"(vl[f]));
    {
        const uint32_t mk = w == 3 ? 1u : 0u;
        auto mark = [&](uint32_t& v) { v = (v & ~mk) | (ob & mk); };
        mark(kh[0]); mark(kh[5]); mark(vh[0]); mark(vh[4]); mark(vh[8]);
    }
    if (w == 3) {
        uint4* hp = &g_halo[bx][wg][0][lane];
        st_ll4(hp, kh[0], kh[1], kh[3], kh[4]); st_ll4(hp + 32, kh[5], kh[6], kh[8], kh[9]);
        st_ll4(hp + 64, vh[0], vh[1], vh[2], vh[3]); st_ll4(hp + 96, vh[4], vh[5], vh[6], vh[7]);
        st_ll4(hp + 128, vh[8], vh[9], kh[2], kh[7]);
    } else {
        const uint32_t a = sb + Q_EOFF + wg * 8192 + w * Q_ESLOT + mj * Q_EROW + mi * 16;
        stsm_x4(a, kh[0], kh[1], kh[3], kh[4]);
        stsm_x4(a + 64, kh[5], kh[6], kh[8], kh[9]);
        stsm_x4(a + 128, vh[0], vh[1], vh[2], vh[3]);
        stsm_x4(a + 192, vh[4], vh[5], vh[6], vh[7]);
        stsm_x4(a + 256, vh[8], vh[9], kh[2], kh[7]);
        __syncwarp();
        if (lane == 0) mbar_arrive(BAR(ex) + 8 * warp);
    }
    TS(9);
    cs_load(0);
#pragma unroll
    for (int f = 0; f < 10; f++) { kl[f] = fold(1, f, 0); if (f >= A_VLO) vl[f] = fold(2, f, 0); }
#pragma unroll
    for (int f = 0; f < 10; f++) { ql[f] = fold(0, f, 0); qh[f] = fold(0, f, 1); }
    auto rs = [&](int i) { return __uint_as_float(lds32(s2u(&s_rstd[wg][16 * w + i]))); };
    const float kx0 = rs(2 * q + (sel0 ? 0 : 8)), kx1 = rs(2 * q + (sel1 ? 1 : 9)), ky0 = rs(2 * q + (sel0 ? 8 : 16)), ky1 = rs(2 * q + (sel1 ? 9 : 17));
    const float rx = SC * rs(8 + g), ry = SC * rs(16 + g), cx0 = rx * kx0, cx1 = rx * kx1, cy0 = ry * ky0, cy1 = ry * ky1;
    uint4 hv[5];
    const uint4* hp = &g_halo[bx - 1][wg][0][lane];
    auto prev = [&] {
        if (w > 0) {
            const uint32_t a = sb + Q_EOFF + wg * 8192 + (w - 1) * Q_ESLOT + mj * Q_EROW + mi * 16;
            mbar_wait(BAR(ex) + 8 * (warp - 1), 0);
            ldsm_x4(hv[0].x, hv[0].y, hv[0].z, hv[0].w, a);
            ldsm_x4(hv[1].x, hv[1].y, hv[1].z, hv[1].w, a + 64);
            ldsm_x4_t(hv[2].x, hv[2].y, hv[2].z, hv[2].w, a + 128);
            ldsm_x4_t(hv[3].x, hv[3].y, hv[3].z, hv[3].w, a + 192);
            ldsm_x2_t(hv[4].x, hv[4].y, a + 256);
            ldsm_x2(hv[4].z, hv[4].w, a + 288 - (lane >> 4) * 32);
        } else if (blk > 0) {
#pragma unroll
            for (int f = 0; f < 5; f++) hv[f] = ld_ll4(hp + 32 * f);
        } else {
#pragma unroll
            for (int f = 0; f < 5; f++) hv[f] = make_uint4(0, 0, 0, 0);
        }
    };
    if (A_HPOS == 0) prev();
    uint32_t vt[10][2];
#pragma unroll
    for (int f = 0; f < 10; f++) { vt[f][0] = movm_t(vl[f]); vt[f][1] = movm_t(vh[f]); }
    if (A_HPOS == 1) prev();
    TS(10);
    auto FA = [](int h) { return h == 0 ? 0 : h == 1 ? 3 : h == 2 ? 5 : 8; };
    auto FH = [](int h) { return h < 2 ? 2 : 7; };
    const uint32_t pm = (sel0 ? 0xFFFFu : 0u) | (sel1 ? 0xFFFF0000u : 0u);
    auto softmax = [&](float x0, float x1, float k0, float k1) {
        float mx = fmaxf(x0, x1);
        mx = fmaxf(mx, __shfl_xor_sync(~0u, mx, 1));
        mx = fmaxf(mx, __shfl_xor_sync(~0u, mx, 2));
        x0 = ex2(x0 - mx); x1 = ex2(x1 - mx);
        float sx = x0 + x1;
        sx += __shfl_xor_sync(~0u, sx, 1);
        sx += __shfl_xor_sync(~0u, sx, 2);
        const float ix = frcp(sx);
        return pack2(x0 * k0 * ix, x1 * k1 * ix);
    };
    uint32_t qm[4][2], py[4];
    float sl[4][2];
#pragma unroll
    for (int h = 0; h < 4; h++) {
        const int fa = FA(h), fb = fa + 1, fh = FH(h);
        const bool mine = (h & 1) ? (q >= 2) : (q < 2);
        qm[h][0] = mine ? ql[fh] : 0u; qm[h][1] = mine ? qh[fh] : 0u;
        float S1[4] = {0.f, 0.f, 0.f, 0.f}, S2[4] = {0.f, 0.f, 0.f, 0.f};
        mma16816(S1, ql[fa], qh[fa], ql[fb], qh[fb], kl[fa], kl[fb]); mma1688(S1, qm[h][0], qm[h][1], kl[fh]);
        mma16816(S2, ql[fa], qh[fa], ql[fb], qh[fb], kh[fa], kh[fb]); mma1688(S2, qm[h][0], qm[h][1], kh[fh]);
        sl[h][0] = S1[0]; sl[h][1] = S1[1];
        py[h] = softmax((sel0 ? S1[2] : S2[2]) * cy0, (sel1 ? S1[3] : S2[3]) * cy1, ky0, ky1);
    }
    TS(11);
    if (w == 0 && blk > 0) {
        int spin = 0;
        while (__any_sync(~0u, ((hv[0].x ^ ob) | (hv[1].x ^ ob) | (hv[2].x ^ ob) | (hv[3].x ^ ob) | (hv[4].x ^ ob)) & 1u) && ++spin < (1 << 18)) {
#pragma unroll
            for (int f = 0; f < 5; f++) hv[f] = ld_ll4(hp + 32 * f);
        }
#pragma unroll
        for (int f = 2; f < 4; f++) hv[f] = make_uint4(movm_t(hv[f].x), movm_t(hv[f].y), movm_t(hv[f].z), movm_t(hv[f].w));
        hv[4].x = movm_t(hv[4].x); hv[4].y = movm_t(hv[4].y);
    }
    const uint32_t kp[10] = {hv[0].x, hv[0].y, hv[4].z, hv[0].z, hv[0].w, hv[1].x, hv[1].y, hv[4].w, hv[1].z, hv[1].w};
    const uint32_t vp[10] = {hv[2].x, hv[2].y, hv[2].z, hv[2].w, hv[3].x, hv[3].y, hv[3].z, hv[3].w, hv[4].x, hv[4].y};
    TS(12);
    const uint4 ko[2] = {ldg_tab(16, tid & 127), ldg_tab(17, tid & 127)};
    const float bx0 = first && sel0 ? -INFINITY : 0.f, bx1 = first && sel1 ? -INFINITY : 0.f;
    float oacc[10][4];
#pragma unroll
    for (int h = 0; h < 4; h++) {
        const int fa = FA(h), fb = fa + 1, fh = FH(h);
        const bool mine = (h & 1) ? (q >= 2) : (q < 2);
        float S0[4] = {0.f, 0.f, 0.f, 0.f};
        mma16816(S0, ql[fa], qh[fa], ql[fb], qh[fb], kp[fa], kp[fb]); mma1688(S0, qm[h][0], qm[h][1], kp[fh]);
        const uint32_t px = softmax(fmaf(sel0 ? S0[0] : sl[h][0], cx0, bx0), fmaf(sel1 ? S0[1] : sl[h][1], cx1, bx1), kx0, kx1);
#pragma unroll
        for (int i = 0; i < 3; i++) {
            const int f = (i == 0) ? fa : (i == 1) ? fb : fh;
            float O[4] = {0.f, 0.f, 0.f, 0.f};
            mma16816(O, px & ~pm, py[h] & pm, 0u, py[h] & ~pm, vt[f][0], vt[f][1]);
            mma1688(O, px & pm, 0u, vp[f]);
            if (i < 2 || !(h & 1) || mine) { oacc[f][0] = O[0]; oacc[f][1] = O[1]; oacc[f][2] = O[2]; oacc[f][3] = O[3]; }
        }
    }
    TS(13);
    constexpr int ON = O_DEPTH + 2;
    uint4 of[ON][5];
    const uint32_t fb = (EPOCH ^ ob) & 1u;
    {
        uint4* dst = &g_of[hg][blk][160 * warp + lane];
#pragma unroll
        for (int k = 0; k < 5; k++) {
            of[0][k] = make_uint4((pack2(oacc[2 * k][0], oacc[2 * k][1]) & ~1u) | fb, pack2(oacc[2 * k][2], oacc[2 * k][3]),
                                  pack2(oacc[2 * k + 1][0], oacc[2 * k + 1][1]), pack2(oacc[2 * k + 1][2], oacc[2 * k + 1][3]));
            st_ll4(dst + 32 * k, of[0][k].x, of[0][k].y, of[0][k].z, of[0][k].w);
        }
    }
    if (wg == 1 && lane == 0) mbar_arrive(BAR(att1));
    TS(14);
    float aw[40];
    auto omma = [&](int j) {
        const uint64_t dm = mkdesc(sb + w_grp(j), 1280, 128, 0);
        wg_fence();
#pragma unroll
        for (int k = 0; k < 5; k++) wgmma_rs80(aw, of[j % ON][k], dm + k * 160, j + k > 0);
        wg_commit();
    };
    mbar_wait(BAR(wfull), 0);
    omma(0);
    named_bar(1 + wg, 128);
    kernel_stage<2>(ko, sb + Q_KDUMP + 2 * wg * KG_RES, &s_kg, 2 * wg, sb + F_EO + wg * 8192, w, lane);
    TS(8);
    const uint4* osrc = &g_of[0][blk][160 * warp + lane];
    auto oload = [&](int j) {
        const uint4* p = osrc + osrc_of(j) * 20480;
#pragma unroll
        for (int k = 0; k < 5; k++) of[j % ON][k] = ld_ll4(p + 32 * k);
    };
    {
        const uint32_t* pp = &g_of[osrc_of(1 + min(lane, 6))][blk][160 * warp + 159].x;
        uint32_t v;
        int spin = 0;
        do { asm volatile("ld.relaxed.gpu.global.u32 %0, [%1];" : "=r"(v) : "l"(pp) : "memory"); } while (__any_sync(~0u, (v & 1u) != fb) && ++spin < (1 << 18));
    }
    TS(15);
    if (O_PASS && wg == 1) mbar_wait(BAR(pass), 0);
#pragma unroll
    for (int j = 1; j <= O_DEPTH; j++) oload(j);
    TS(16);
#pragma unroll
    for (int j = 1; j < 8; j++) {
        if (j == 3 || j == 7) mbar_wait(BAR(wfull) + 8 * ((j + 1) >> 2), 0);
        const uint4* f = of[j % ON];
        int spin = 0;
        while (__any_sync(~0u, ((f[0].x ^ fb) | (f[1].x ^ fb) | (f[2].x ^ fb) | (f[3].x ^ fb) | (f[4].x ^ fb)) & 1u) && ++spin < (1 << 18)) oload(j);
        if (j + O_DEPTH < 8) { wg_wait<1>(); oload(j + O_DEPTH); }
        if (j == 7 && lane == 0) mbar_arrive(BAR(soon) + 8 * wg);
        if (j == O_PASS && wg == 0 && lane == 0) mbar_arrive(BAR(pass));
        if (j == O_TPOS) { wg_wait<1>(); conv_tables(); }
        if (j == 1) TS(17);
        if (j == 5) TS(18);
        omma(j);
    }
    wg_wait<2>();
    uint32_t res[20];
    mbar_wait(BAR(res), 0);
    const uint32_t ta = (8 * (mi >> 1) + mj) * 128 + (((2 * w + (mi & 1)) ^ mj) << 4);
    if (layer == 0) {
        const int tok = 16 * w + 8 * (mi & 1) + mj;
#pragma unroll
        for (int k = 0; k < 4; k++)
            ldsm_x4(res[4 * k], res[4 * k + 1], res[4 * k + 2], res[4 * k + 3], sb + W_RES + wg * 10240 + tok * 128 + (((2 * k + (mi >> 1)) ^ mj) << 4));
        ldsm_x4(res[16], res[17], res[18], res[19], sb + W_RES + wg * 10240 + 8192 + tok * 32 + (((mi >> 1) ^ (mj >> 2)) << 4));
    } else {
#pragma unroll
        for (int k = 0; k < 5; k++) ldsm_x4_t(res[4 * k], res[4 * k + 1], res[4 * k + 2], res[4 * k + 3], sb + W_RES + wg * 10240 + k * 2048 + ta);
    }
    mbar_wait(BAR(qdone), 0);
    wg_wait<0>();
    TS(19);
#pragma unroll
    for (int i = 0; i < 20; i++) {
        const uint32_t y = pack2(aw[2 * i], aw[2 * i + 1]);
        asm("add.rn.bf16x2 %0, %0, %1;" : "+r"(res[i]) : "r"(y));
    }
    auto stage_out = [&] {
        const uint32_t mk = (g & 3) ? 0u : 0x00010001u;
#pragma unroll
        for (int k = 0; k < 5; k++) {
            uint32_t m[4];
#pragma unroll
            for (int i = 0; i < 4; i++) m[i] = (res[4 * k + i] & ~mk) | (mk & (0u - ob));
            stsm_x4_t(sb + W_OUT + wg * 10240 + k * 2048 + ta, m[0], m[1], m[2], m[3]);
        }
        fence_async_smem();
        named_bar(1 + wg, 128);
        if (w == 0 && elect_one()) {
            asm volatile("cp.async.bulk.tensor.2d.global.shared::cta.bulk_group [%0, {%2, %3}], [%1];"
                         ::"l"(TMAP(7)), "r"(sb + W_OUT + wg * 10240), "r"(1024 * wg + 64 * blk), "r"(hg * 80) : "memory");
            bulk_commit();
            mbar_arrive(BAR(staged));
        }
        __syncwarp();
        TS(20);
    };
    if (!S_FIRST) stage_out();
    {
        float sm[4] = {0.f, 0.f, 0.f, 0.f}, d0[4] = {0.f, 0.f, 0.f, 0.f}, d1[4] = {0.f, 0.f, 0.f, 0.f};
#pragma unroll
        for (int k = 0; k < 5; k++) {
            mma16816(sm, res[4 * k], res[4 * k + 1], res[4 * k + 2], res[4 * k + 3], 0x3F803F80u, 0x3F803F80u);
            mma16816(d0, res[4 * k], res[4 * k + 1], res[4 * k + 2], res[4 * k + 3], res[4 * k], res[4 * k + 2]);
            mma16816(d1, res[4 * k], res[4 * k + 1], res[4 * k + 2], res[4 * k + 3], res[4 * k + 1], res[4 * k + 3]);
        }
        if (q == (g >> 1))
            st_ll4(&g_sp2[blk][warp][hg][g], (__float_as_uint(sm[0]) & ~1u) | ob, __float_as_uint((g & 1) ? d0[1] : d0[0]), __float_as_uint(sm[2]),
                   __float_as_uint((g & 1) ? d1[3] : d1[2]));
    }
    TS(23);
    if (S_FIRST) stage_out();
    if (layer) {
#pragma unroll
        for (int k = 0; k < 5; k++) stsm_x4_t(sb + W_RES + wg * 10240 + k * 2048 + ta, res[4 * k], res[4 * k + 1], res[4 * k + 2], res[4 * k + 3]);
    }
    if (O_TPOS == 9) conv_tables();
    TS(22);
    TS_PHASE(2 * layer + 1);
    TS(0);
    indices();
    conv_wg<2>(5 * bx + 2 * (warp >> 2), layer, sb + F_EO + (warp >> 2) * 8192, sb + (warp >> 2) * Q_SB, sb + F_S23, s2u(&s_kg.kexp[2 * (warp >> 2)]),
               s2u(&s_epoch), sb + 3 * Q_SB, BAR(st), warp, lane, fa1, ftw, [&] {
        if ((warp & 3) == 0 && elect_one()) {
            asm volatile("cp.async.bulk.wait_group.read 0;" ::: "memory");
            if (layer == 0) { mbar_arrive_cta(BAR(wfree), 0); mbar_arrive_cta(BAR(wfree), 1); }
        }
        __syncwarp();
    }, [&] {
        if (warp == 0) {
            const bf16* pp = g_x1T + (size_t)(5 * bx + 4) * XP + 64 * lane + 60;
            mbar_wait(BAR(staged), 0);
            uint32_t v;
            int spin = 0;
            if (X_HINT) do { asm volatile("ld.relaxed.gpu.global.u32 %0, [%1];" : "=r"(v) : "l"(pp) : "memory"); } while (__any_sync(~0u, ~(v ^ layer) & 1u) && ++spin < (1 << 18));
            if (lane == 0) mbar_arrive(BAR(ardy));
        } else {
            mbar_wait(BAR(ardy), 0);
        }
    }, [] {} TS_PASS);
    conv_done();
    asm volatile("setmaxnreg.dec.sync.aligned.u32 168;");
    }
    named_bar(1 + (warp >> 2), 128);
    asm volatile("setmaxnreg.dec.sync.aligned.u32 %0;" ::"n"(504 - 2 * R_CONS));
    }
    indices();
    const int cq = 4 * (warp >> 1) + (lane & 3), tg = 8 * (warp & 1) + (lane >> 2);
    const uint32_t fb = ~EPOCH & 1u;
    uint2 xr[4][2];
    __syncthreads();
    if (tid < 320) {
#pragma unroll
        for (int i = 0; i < 8; i++) {
            const int ch = 4 * cq + (i >> 1);
            asm volatile("ld.shared.v2.u32 {%0, %1}, [%2];" : "=r"(xr[i >> 1][i & 1].x), "=r"(xr[i >> 1][i & 1].y)
                         : "r"(sb + W_RES + (i & 1) * 10240 + ch * 128 + (((tg >> 1) ^ (ch & 7)) << 4) + (tg & 1) * 8) : "memory");
        }
    }
    if (tid < 320) {
        const uint4* src = &g_of[hg][blk][64 * cq + tg];
        uint4 v[4];
#pragma unroll
        for (int i = 0; i < 4; i++) v[i] = make_uint4(~fb, 0, 0, 0);
        int spin = 0;
        while (true) {
#pragma unroll
            for (int i = 0; i < 4; i++) if ((v[i].x ^ fb) & 1u) v[i] = ld_ll4(src + 16 * i);
            if (!(((v[0].x ^ fb) | (v[1].x ^ fb) | (v[2].x ^ fb) | (v[3].x ^ fb)) & 1u) || ++spin >= (1 << 18)) break;
        }
        TS(21);
#pragma unroll
        for (int i = 0; i < 16; i++) asm("add.rn.bf16x2 %0, %0, %1;" : "+r"(u4r(v[i >> 2], i & 3)) : "r"((i & 1) ? xr[i >> 2][(i >> 1) & 1].y : xr[i >> 2][(i >> 1) & 1].x));
#pragma unroll
        for (int j = 0; j < 8; j++) {
            const uint32_t sel = (j & 2) ? 0x7632 : 0x5410;
            const int k = 2 * (j & 1) + (j >> 2);
            asm volatile("st.shared.v2.u32 [%0], {%1, %2};" ::"r"(sb + 2 * Q_SB + (16 * j + tg) * 160 + cq * 8),
                         "r"(__byte_perm(u4(v[0], k), u4(v[1], k), sel)), "r"(__byte_perm(u4(v[2], k), u4(v[3], k), sel)) : "memory");
        }
        fence_async_smem();
    }
    __syncthreads();
    if (warp == 0 && elect_one()) {
        asm volatile("cp.async.bulk.tensor.3d.global.shared::cta.bulk_group [%0, {%2, %3, 0}], [%1];" ::"l"(TMAP(9)), "r"(sb + 2 * Q_SB), "r"(80 * hg), "r"(16 * blk) : "memory");
        bulk_commit();
        asm volatile("cp.async.bulk.wait_group.read 0;" ::: "memory");
    }
    if (bx == 0 && tid == 0) g_epoch = EPOCH + 1;
    TS(22);
    TS_END;
}
typedef CUresult (*EncodeTiledFn)(CUtensorMap*, CUtensorMapDataType, cuuint32_t, void*, const cuuint64_t*, const cuuint64_t*, const cuuint32_t*,
                                  const cuuint32_t*, CUtensorMapInterleave, CUtensorMapSwizzle, CUtensorMapL2promotion, CUtensorMapFloatOOBfill);

static void make_map(EncodeTiledFn enc, CUtensorMap* m, const void* base, int rank, const cuuint64_t* dims, const cuuint64_t* strides,
                     const cuuint32_t* box, CUtensorMapSwizzle sw) {
    cuuint32_t es[4] = {1, 1, 1, 1};
    enc(m, CU_TENSOR_MAP_DATA_TYPE_BFLOAT16, rank, (void*)base, dims, strides, box, es, CU_TENSOR_MAP_INTERLEAVE_NONE, sw,
        sw == CU_TENSOR_MAP_SWIZZLE_128B ? CU_TENSOR_MAP_L2_PROMOTION_L2_128B : CU_TENSOR_MAP_L2_PROMOTION_NONE, CU_TENSOR_MAP_FLOAT_OOB_FILL_NONE);
}

template <typename... KArgs, typename... Args>
static void launch(void (*kern)(KArgs...), int grid, int block, int smem, int cluster, bool pdl, Args... args) {
    cudaLaunchConfig_t cfg = {};
    cfg.gridDim = dim3(grid); cfg.blockDim = dim3(block); cfg.dynamicSmemBytes = smem; cfg.stream = cudaStreamPerThread;
    cudaLaunchAttribute at[2];
    int n = 0;
    if (cluster > 1) { at[n].id = cudaLaunchAttributeClusterDimension; at[n].val.clusterDim.x = cluster; at[n].val.clusterDim.y = 1; at[n].val.clusterDim.z = 1; n++; }
    if (pdl) { at[n].id = cudaLaunchAttributeProgrammaticStreamSerialization; at[n].val.programmaticStreamSerializationAllowed = 1; n++; }
    cfg.attrs = at; cfg.numAttrs = n;
    cudaLaunchKernelEx(&cfg, kern, KArgs(args)...);
}

struct HostState {
    bool ready = false;
    const void* key[4] = {nullptr, nullptr, nullptr, nullptr};
    CUtensorMap mX[2], mRes[2], mW, mWr, mWo, mOut, mFin, mResA;
    bf16 *x1T, *x2T;
    unsigned* epoch;
};

extern "C" void kernel_launch(void* const* d_in, const int* in_sizes, int n_in, void* d_out, int out_size) {
    const bf16* x = (const bf16*)d_in[0];
    const bf16* wqkv = (const bf16*)d_in[1];
    const bf16* wo = (const bf16*)d_in[2];
    const bf16* lar = (const bf16*)d_in[4];
    const bf16* aim = (const bf16*)d_in[5];
    const bf16* cre = (const bf16*)d_in[6];
    const bf16* cim = (const bf16*)d_in[7];
    const bf16* logdt = (const bf16*)d_in[8];
    const bf16* dskip = (const bf16*)d_in[9];
    static HostState hs;
    if (!hs.ready || hs.key[0] != wqkv || hs.key[1] != wo || hs.key[2] != x || hs.key[3] != d_out) {
        void* fn = nullptr;
        cudaDriverEntryPointQueryResult qr;
        cudaGetDriverEntryPoint("cuTensorMapEncodeTiled", &fn, cudaEnableDefault, &qr);
        EncodeTiledFn enc = (EncodeTiledFn)fn;
        cudaGetSymbolAddress((void**)&hs.epoch, g_epoch);
        cudaGetSymbolAddress((void**)&hs.x1T, g_x1T);
        cudaGetSymbolAddress((void**)&hs.x2T, g_x2T);
        {
            cuuint64_t d[3] = {DM, SEQ / 2, 2}, s[2] = {DM * 4, DM * 2};
            cuuint32_t b[3] = {64, 64, 2}, ba[3] = {64, 64, 1}, br[3] = {16, 64, 1};
            make_map(enc, &hs.mX[0], x, 3, d, s, b, CU_TENSOR_MAP_SWIZZLE_128B);
            make_map(enc, &hs.mResA, x, 3, d, s, ba, CU_TENSOR_MAP_SWIZZLE_128B);
            make_map(enc, &hs.mRes[0], x, 3, d, s, br, CU_TENSOR_MAP_SWIZZLE_32B);
            cuuint64_t d2[3] = {SEQ / 2, DM, 2}, s2[2] = {XP * 2, SEQ};
            cuuint32_t b2[3] = {64, 80, 2};
            make_map(enc, &hs.mX[1], hs.x2T, 3, d2, s2, b, CU_TENSOR_MAP_SWIZZLE_128B);
            make_map(enc, &hs.mRes[1], hs.x2T, 3, d2, s2, b2, CU_TENSOR_MAP_SWIZZLE_128B);
            cuuint64_t d3[2] = {SEQ, DM};
            make_map(enc, &hs.mOut, hs.x1T, 2, d3, s2, b2, CU_TENSOR_MAP_SWIZZLE_128B);
        }
        { cuuint64_t d[2] = {3 * DM, DM}, s[1] = {3 * DM * 2}; cuuint32_t b[2] = {64, 32};
          make_map(enc, &hs.mW, wqkv, 2, d, s, b, CU_TENSOR_MAP_SWIZZLE_128B); }
        { cuuint64_t d[3] = {DM, DM, 3}, s[2] = {3 * DM * 2, DM * 2}; cuuint32_t b[3] = {16, 32, 3};
          make_map(enc, &hs.mWr, wqkv, 3, d, s, b, CU_TENSOR_MAP_SWIZZLE_32B); }
        { cuuint64_t d[4] = {8, 8, DM / 8, DM / 8}, s[3] = {DM * 2, 16, DM * 16}; cuuint32_t b[4] = {8, 8, 10, 5};
          make_map(enc, &hs.mWo, wo, 4, d, s, b, CU_TENSOR_MAP_SWIZZLE_NONE); }
        { cuuint64_t d[3] = {DM, SEQ / 8, 8}, s[2] = {DM * 16, DM * 2}; cuuint32_t b[3] = {80, 16, 8};
          make_map(enc, &hs.mFin, d_out, 3, d, s, b, CU_TENSOR_MAP_SWIZZLE_NONE); }
        cudaFuncSetAttribute(fused_kernel, cudaFuncAttributeMaxDynamicSharedMemorySize, Q_SMEM);
        hs.key[0] = wqkv; hs.key[1] = wo; hs.key[2] = x; hs.key[3] = d_out;
        hs.ready = true;
    }
    const SsmParams sp = {lar, aim, cre, cim, logdt, dskip, hs.epoch};
    launch(fused_kernel, 128, 384, Q_SMEM, 2, false, sp, hs.mX[0], hs.mX[1], hs.mW, hs.mWr, hs.mRes[0], hs.mRes[1], hs.mOut, hs.mWo, hs.mFin, hs.mResA);
}
```

```cpp
#include <cuda_runtime.h>
#include <cuda.h>
#include <cuda_bf16.h>
#include <cuda_fp16.h>
#include <stdint.h>

typedef __nv_bfloat16 bf16;

constexpr int SEQ = 2048;
constexpr int DM  = 640;
constexpr int XP  = SEQ + 64;
constexpr int NMODE = 192;

__device__ __forceinline__ uint32_t s2u(const void* p) { return (uint32_t)__cvta_generic_to_shared(p); }
__device__ __forceinline__ void mbar_init(uint32_t b, int c) { asm volatile("mbarrier.init.shared::cta.b64 [%0], %1;" ::"r"(b), "r"(c)); }
__device__ __forceinline__ void mbar_expect(uint32_t b, uint32_t bytes) { asm volatile("mbarrier.arrive.expect_tx.shared::cta.b64 _, [%0], %1;" ::"r"(b), "r"(bytes) : "memory"); }
__device__ __forceinline__ void mbar_arrive(uint32_t b) { asm volatile("mbarrier.arrive.shared::cta.b64 _, [%0];" ::"r"(b) : "memory"); }
__device__ __forceinline__ void mbar_arrive_cta(uint32_t b, uint32_t cta) {
    asm volatile("{\n.reg .b32 ra;\nmapa.shared::cluster.u32 ra, %0, %1;\nmbarrier.arrive.shared::cluster.b64 _, [ra];\n}" ::"r"(b), "r"(cta) : "memory");
}
__device__ __forceinline__ void mbar_wait(uint32_t b, uint32_t ph) {
#ifdef M_PLAIN
    asm volatile("{\n.reg .pred p;\nW: mbarrier.try_wait.parity.shared::cta.b64 p, [%0], %1;\n@!p bra W;\n}" ::"r"(b), "r"(ph) : "memory");
    return;
#endif
    asm volatile("{\n.reg .pred p;\n.reg .u32 n;\nmbarrier.try_wait.parity.shared::cta.b64 p, [%0], %1;\n@p bra D;\nmov.u32 n, 0;\n"
                 "W: mbarrier.try_wait.parity.shared::cta.b64 p, [%0], %1;\n@p bra D;\nadd.u32 n, n, 1;\nsetp.lt.u32 p, n, 4194304;\n@p bra W;\ntrap;\nD:\n}"
                 ::"r"(b), "r"(ph) : "memory");
}
__device__ __forceinline__ void fence_mbar_init() { asm volatile("fence.mbarrier_init.release.cluster;" ::: "memory"); }
__device__ __forceinline__ void cluster_sync() { asm volatile("barrier.cluster.arrive.aligned;\nbarrier.cluster.wait.aligned;" ::: "memory"); }
__device__ __forceinline__ void pdl_wait() { asm volatile("griddepcontrol.wait;" ::: "memory"); }
__device__ __forceinline__ void pdl_launch() { asm volatile("griddepcontrol.launch_dependents;" ::: "memory"); }
__device__ __forceinline__ void named_bar(int id, int n) { asm volatile("bar.sync %0, %1;" ::"r"(id), "r"(n) : "memory"); }
__device__ __forceinline__ void fence_async_smem() { asm volatile("fence.proxy.async.shared::cta;" ::: "memory"); }

__device__ __forceinline__ void tma2d(uint32_t dst, const CUtensorMap* m, int c0, int c1, uint32_t bar) {
    asm volatile("cp.async.bulk.tensor.2d.shared::cluster.global.mbarrier::complete_tx::bytes [%0], [%1, {%3, %4}], [%2];"
                 ::"r"(dst), "l"(m), "r"(bar), "r"(c0), "r"(c1) : "memory");
}
__device__ __forceinline__ void tma2d_mc(uint32_t dst, const CUtensorMap* m, int c0, int c1, uint32_t bar, uint16_t mask) {
    asm volatile("cp.async.bulk.tensor.2d.shared::cluster.global.mbarrier::complete_tx::bytes.multicast::cluster [%0], [%1, {%3, %4}], [%2], %5;"
                 ::"r"(dst), "l"(m), "r"(bar), "r"(c0), "r"(c1), "h"(mask) : "memory");
}
__device__ __forceinline__ void tma3d(uint32_t dst, const CUtensorMap* m, int c0, int c1, int c2, uint32_t bar) {
    asm volatile("cp.async.bulk.tensor.3d.shared::cluster.global.mbarrier::complete_tx::bytes [%0], [%1, {%3, %4, %5}], [%2];"
                 ::"r"(dst), "l"(m), "r"(bar), "r"(c0), "r"(c1), "r"(c2) : "memory");
}
__device__ __forceinline__ void tma3d_mc(uint32_t dst, const CUtensorMap* m, int c0, int c1, int c2, uint32_t bar, uint16_t mask) {
    asm volatile("cp.async.bulk.tensor.3d.shared::cluster.global.mbarrier::complete_tx::bytes.multicast::cluster [%0], [%1, {%3, %4, %5}], [%2], %6;"
                 ::"r"(dst), "l"(m), "r"(bar), "r"(c0), "r"(c1), "r"(c2), "h"(mask) : "memory");
}
__device__ __forceinline__ void bulk_g2s(uint32_t dst, const void* src, uint32_t bytes, uint32_t bar) {
    asm volatile("cp.async.bulk.shared::cluster.global.mbarrier::complete_tx::bytes [%0], [%1], %2, [%3];"
                 ::"r"(dst), "l"(src), "r"(bytes), "r"(bar) : "memory");
}
__device__ __forceinline__ void bulk_g2s_mc(uint32_t dst, const void* src, uint32_t bytes, uint32_t bar, uint16_t mask) {
    asm volatile("cp.async.bulk.shared::cluster.global.mbarrier::complete_tx::bytes.multicast::cluster [%0], [%1], %2, [%3], %4;"
                 ::"r"(dst), "l"(src), "r"(bytes), "r"(bar), "h"(mask) : "memory");
}
__device__ __forceinline__ void prefetch_l2(const void* p, uint32_t bytes) { asm volatile("cp.async.bulk.prefetch.L2.global [%0], %1;" ::"l"(p), "r"(bytes) : "memory"); }
__device__ __forceinline__ void prefetch_tmap(const CUtensorMap* m) { asm volatile("prefetch.tensormap [%0];" ::"l"(m) : "memory"); }

__device__ __forceinline__ void wg_fence() { asm volatile("wgmma.fence.sync.aligned;" ::: "memory"); }
__device__ __forceinline__ void wg_commit() { asm volatile("wgmma.commit_group.sync.aligned;" ::: "memory"); }
template <int N> __device__ __forceinline__ void wg_wait() { asm volatile("wgmma.wait_group.sync.aligned %0;" ::"n"(N) : "memory"); }
__device__ __forceinline__ uint64_t mkdesc(uint32_t addr, uint32_t lbo, uint32_t sbo, uint32_t mode) {
    return (uint64_t)((addr & 0x3FFFF) >> 4) | ((uint64_t)(lbo >> 4) << 16) | ((uint64_t)(sbo >> 4) << 32) | ((uint64_t)mode << 62);
}

__device__ __forceinline__ void mma16816(float (&c)[4], uint32_t a0, uint32_t a1, uint32_t a2, uint32_t a3, uint32_t b0, uint32_t b1) {
    asm("mma.sync.aligned.m16n8k16.row.col.f32.bf16.bf16.f32 {%0,%1,%2,%3},{%4,%5,%6,%7},{%8,%9},{%0,%1,%2,%3};"
                 : "+f"(c[0]), "+f"(c[1]), "+f"(c[2]), "+f"(c[3]) : "r"(a0), "r"(a1), "r"(a2), "r"(a3), "r"(b0), "r"(b1));
}
__device__ __forceinline__ void mma1688(float (&c)[4], uint32_t a0, uint32_t a1, uint32_t b0) {
    asm("mma.sync.aligned.m16n8k8.row.col.f32.bf16.bf16.f32 {%0,%1,%2,%3},{%4,%5},{%6},{%0,%1,%2,%3};"
                 : "+f"(c[0]), "+f"(c[1]), "+f"(c[2]), "+f"(c[3]) : "r"(a0), "r"(a1), "r"(b0));
}
__device__ __forceinline__ void ldsm_x4(uint32_t& r0, uint32_t& r1, uint32_t& r2, uint32_t& r3, uint32_t a) {
    asm volatile("ldmatrix.sync.aligned.m8n8.x4.shared.b16 {%0,%1,%2,%3}, [%4];" : "=r"(r0), "=r"(r1), "=r"(r2), "=r"(r3) : "r"(a) : "memory");
}
__device__ __forceinline__ void ldsm_x4_t(uint32_t& r0, uint32_t& r1, uint32_t& r2, uint32_t& r3, uint32_t a) {
    asm volatile("ldmatrix.sync.aligned.m8n8.x4.trans.shared.b16 {%0,%1,%2,%3}, [%4];" : "=r"(r0), "=r"(r1), "=r"(r2), "=r"(r3) : "r"(a) : "memory");
}
__device__ __forceinline__ void ldsm_x2(uint32_t& r0, uint32_t& r1, uint32_t a) {
    asm volatile("ldmatrix.sync.aligned.m8n8.x2.shared.b16 {%0,%1}, [%2];" : "=r"(r0), "=r"(r1) : "r"(a) : "memory");
}
__device__ __forceinline__ void ldsm_x2_t(uint32_t& r0, uint32_t& r1, uint32_t a) {
    asm volatile("ldmatrix.sync.aligned.m8n8.x2.trans.shared.b16 {%0,%1}, [%2];" : "=r"(r0), "=r"(r1) : "r"(a) : "memory");
}
__device__ __forceinline__ void stsm_x4(uint32_t a, uint32_t r0, uint32_t r1, uint32_t r2, uint32_t r3) {
    asm volatile("stmatrix.sync.aligned.m8n8.x4.shared.b16 [%0], {%1,%2,%3,%4};" ::"r"(a), "r"(r0), "r"(r1), "r"(r2), "r"(r3) : "memory");
}
__device__ __forceinline__ void stsm_x4_t(uint32_t a, uint32_t r0, uint32_t r1, uint32_t r2, uint32_t r3) {
    asm volatile("stmatrix.sync.aligned.m8n8.x4.trans.shared.b16 [%0], {%1,%2,%3,%4};" ::"r"(a), "r"(r0), "r"(r1), "r"(r2), "r"(r3) : "memory");
}
__device__ __forceinline__ void stsm_x2(uint32_t a, uint32_t r0, uint32_t r1) {
    asm volatile("stmatrix.sync.aligned.m8n8.x2.shared.b16 [%0], {%1,%2};" ::"r"(a), "r"(r0), "r"(r1) : "memory");
}
__device__ __forceinline__ uint32_t movm_t(uint32_t a) {
    uint32_t d;
    asm volatile("movmatrix.sync.aligned.m8n8.trans.b16 %0, %1;" : "=r"(d) : "r"(a));
    return d;
}
__device__ __forceinline__ uint32_t lds32(uint32_t a) { uint32_t v; asm volatile("ld.shared.u32 %0, [%1];" : "=r"(v) : "r"(a) : "memory"); return v; }
__device__ __forceinline__ uint32_t ldsv32(uint32_t a) { uint32_t v; asm volatile("ld.volatile.shared.u32 %0, [%1];" : "=r"(v) : "r"(a) : "memory"); return v; }
__device__ __forceinline__ void sts32(uint32_t a, uint32_t v) { asm volatile("st.shared.u32 [%0], %1;" ::"r"(a), "r"(v) : "memory"); }
__device__ __forceinline__ uint4 lds128(uint32_t a) { uint4 v; asm volatile("ld.shared.v4.u32 {%0,%1,%2,%3}, [%4];" : "=r"(v.x), "=r"(v.y), "=r"(v.z), "=r"(v.w) : "r"(a) : "memory"); return v; }
__device__ __forceinline__ void sts128(uint32_t a, uint4 v) { asm volatile("st.shared.v4.u32 [%0], {%1,%2,%3,%4};" ::"r"(a), "r"(v.x), "r"(v.y), "r"(v.z), "r"(v.w) : "memory"); }

__device__ __forceinline__ void stg128(void* p, uint4 v) { asm volatile("st.global.v4.u32 [%0], {%1,%2,%3,%4};" ::"l"(p), "r"(v.x), "r"(v.y), "r"(v.z), "r"(v.w) : "memory"); }

__device__ __forceinline__ uint4 ldg128(const void* p) { uint4 v; asm volatile("ld.global.v4.u32 {%0,%1,%2,%3}, [%4];" : "=r"(v.x), "=r"(v.y), "=r"(v.z), "=r"(v.w) : "l"(p) : "memory"); return v; }
__device__ __forceinline__ uint2 ldg64(const void* p) { uint2 v; asm volatile("ld.global.v2.u32 {%0,%1}, [%2];" : "=r"(v.x), "=r"(v.y) : "l"(p) : "memory"); return v; }
__device__ __forceinline__ uint32_t ldg32(const void* p) { uint32_t v; asm volatile("ld.global.u32 %0, [%1];" : "=r"(v) : "l"(p) : "memory"); return v; }

__device__ __forceinline__ uint32_t pack2(float lo, float hi) {
    uint32_t r;
    asm("cvt.rn.bf16x2.f32 %0, %1, %2;" : "=r"(r) : "f"(hi), "f"(lo));
    return r;
}
__device__ __forceinline__ float bf_lo(uint32_t v) { return __uint_as_float(v << 16); }
__device__ __forceinline__ float bf_hi(uint32_t v) { return __uint_as_float(v & 0xFFFF0000u); }
__device__ __forceinline__ float rbf(float x) { return __uint_as_float(pack2(0.f, x) & 0xFFFF0000u); }
__device__ __forceinline__ float ex2(float x) { float r; asm("ex2.approx.ftz.f32 %0, %1;" : "=f"(r) : "f"(x)); return r; }

__device__ __forceinline__ float2 ln_finish(float sum, float sumsq) {
    const float m = sum * (1.0f / DM);
    const float v = fmaxf(fmaf(sumsq, 1.0f / DM, -m * m), 0.f);
    float s, r;
    asm("sqrt.approx.ftz.f32 %0, %1;" : "=f"(s) : "f"(rbf(rbf(v) + 1e-5f)));
    asm("rcp.approx.ftz.f32 %0, %1;" : "=f"(r) : "f"(rbf(s)));
    return make_float2(m, r);
}
__device__ __forceinline__ uint32_t ln_finish_packed(float sum, float sumsq) {
    const float m = sum * (1.0f / DM);
    const float v = fmaxf(fmaf(sumsq, 1.0f / DM, -m * m), 0.f);
    float s;
    asm("sqrt.approx.ftz.f32 %0, %1;" : "=f"(s) : "f"(rbf(rbf(v) + 1e-5f)));
    return pack2(s, m);
}
__device__ __forceinline__ float frsq(float x) { float r; asm("rsqrt.approx.ftz.f32 %0, %1;" : "=f"(r) : "f"(x)); return r; }
__device__ __forceinline__ float frcp(float x) { float r; asm("rcp.approx.ftz.f32 %0, %1;" : "=f"(r) : "f"(x)); return r; }
__device__ __forceinline__ bool elect_one() {
    uint32_t p;
    asm volatile("{\n.reg .pred p;\nelect.sync _|p, 0xffffffff;\nselp.u32 %0, 1, 0, p;\n}" : "=r"(p));
    return p != 0;
}
__device__ __forceinline__ void cluster_arrive_relaxed() { asm volatile("barrier.cluster.arrive.relaxed.aligned;" ::: "memory"); }
__device__ __forceinline__ void cluster_wait() { asm volatile("barrier.cluster.wait.aligned;" ::: "memory"); }
__device__ __forceinline__ unsigned long long ld_ll(const unsigned long long* p) {
    unsigned long long v;
    asm volatile("ld.relaxed.gpu.global.b64 %0, [%1];" : "=l"(v) : "l"(p) : "memory");
    return v;
}
__device__ __forceinline__ void st_ll(unsigned long long* p, uint32_t payload, uint32_t tag) {
    const unsigned long long v = (unsigned long long)payload | ((unsigned long long)tag << 32);
    asm volatile("st.relaxed.gpu.global.b64 [%0], %1;" ::"l"(p), "l"(v) : "memory");
}
__device__ __forceinline__ uint4 ld_ll4(const uint4* p) {
    uint4 v;
    asm volatile("{\n.reg .b128 t;\n.reg .b64 a, b;\nld.relaxed.gpu.global.b128 t, [%4];\nmov.b128 {a, b}, t;\nmov.b64 {%0, %1}, a;\nmov.b64 {%2, %3}, b;\n}"
                 : "=r"(v.x), "=r"(v.y), "=r"(v.z), "=r"(v.w) : "l"(p) : "memory");
    return v;
}
__device__ __forceinline__ void st_ll4(uint4* p, uint32_t x, uint32_t y, uint32_t z, uint32_t w) {
    asm volatile("{\n.reg .b128 t;\n.reg .b64 a, b;\nmov.b64 a, {%1, %2};\nmov.b64 b, {%3, %4};\nmov.b128 t, {a, b};\nst.relaxed.gpu.global.b128 [%0], t;\n}"
                 ::"l"(p), "r"(x), "r"(y), "r"(z), "r"(w) : "memory");
}

__device__ __forceinline__ void bulk_s2g(void* dst, uint32_t src, uint32_t bytes) {
    asm volatile("cp.async.bulk.global.shared::cta.bulk_group [%0], [%1], %2;" ::"l"(dst), "r"(src), "r"(bytes) : "memory");
}
__device__ __forceinline__ void bulk_commit() { asm volatile("cp.async.bulk.commit_group;" ::: "memory"); }
__device__ __forceinline__ void bulk_wait() { asm volatile("cp.async.bulk.wait_group 0;" ::: "memory"); }
__device__ __forceinline__ void fence_async_global() { asm volatile("fence.proxy.async.global;" ::: "memory"); }
__device__ __forceinline__ void fence_release() { asm volatile("fence.release.gpu;" ::: "memory"); }
__device__ __forceinline__ void fence_acquire() { asm volatile("fence.acquire.gpu;" ::: "memory"); }
__device__ __forceinline__ void ll_check5(uint4 (&f)[5], const uint4* p, uint32_t mark) {
#define LL_LD(i, a, b, c, d) "ld.relaxed.gpu.global.b128 q, [%20 + " #i "];\nmov.b128 {u, v}, q;\nmov.b64 {%" #a ", %" #b "}, u;\nmov.b64 {%" #c ", %" #d "}, v;\n"
    asm volatile("{\n.reg .pred p;\n.reg .b32 t, n, m;\n.reg .b128 q;\n.reg .b64 u, v;\nmov.u32 n, 0x7FFFF;\n"
                 "L:\nlop3.b32 t, %0, %4, %21, 0x7E;\nlop3.b32 t, t, %8, %21, 0xF6;\nlop3.b32 t, t, %12, %21, 0xF6;\nlop3.b32 t, t, %16, %21, 0xF6;\n"
                 "shr.u32 m, n, 18;\nand.b32 t, t, m;\nsetp.ne.u32 p, t, 0;\nvote.sync.any.pred p, p, 0xffffffff;\n@!p bra.uni D;\n"
                 LL_LD(0, 0, 1, 2, 3) LL_LD(512, 4, 5, 6, 7) LL_LD(1024, 8, 9, 10, 11) LL_LD(1536, 12, 13, 14, 15) LL_LD(2048, 16, 17, 18, 19)
                 "sub.u32 n, n, 1;\nbra.uni L;\nD:\n}"
                 : "+r"(f[0].x), "+r"(f[0].y), "+r"(f[0].z), "+r"(f[0].w), "+r"(f[1].x), "+r"(f[1].y), "+r"(f[1].z), "+r"(f[1].w), "+r"(f[2].x), "+r"(f[2].y),
                   "+r"(f[2].z), "+r"(f[2].w), "+r"(f[3].x), "+r"(f[3].y), "+r"(f[3].z), "+r"(f[3].w), "+r"(f[4].x), "+r"(f[4].y), "+r"(f[4].z), "+r"(f[4].w)
                 : "l"(p), "r"(mark) : "memory");
}
template<int TA, int TB>
__device__ __forceinline__ void wgmma_n192(float (&d)[96], uint64_t da, uint64_t db, int scale_d) {
  asm volatile("{\n.reg .pred p;\nsetp.ne.b32 p, %98, 0;\n"
    "wgmma.mma_async.sync.aligned.m64n192k16.f32.bf16.bf16 "
    "{%0, %1, %2, %3, %4, %5, %6, %7, %8, %9, %10, %11, %12, %13, %14, %15, %16, %17, %18, %19, %20, %21, %22, %23, %24, %25, %26, %27, %28, %29, %30, %31, %32, %33, %34, %35, %36, %37, %38, %39, %40, %41, %42, %43, %44, %45, %46, %47, %48, %49, %50, %51, %52, %53, %54, %55, %56, %57, %58, %59, %60, %61, %62, %63, %64, %65, %66, %67, %68, %69, %70, %71, %72, %73, %74, %75, %76, %77, %78, %79, %80, %81, %82, %83, %84, %85, %86, %87, %88, %89, %90, %91, %92, %93, %94, %95}, %96, %97, p, 1, 1, %99, %100;\n}\n"
    : "+f"(d[0]), "+f"(d[1]), "+f"(d[2]), "+f"(d[3]), "+f"(d[4]), "+f"(d[5]), "+f"(d[6]), "+f"(d[7]), "+f"(d[8]), "+f"(d[9]), "+f"(d[10]), "+f"(d[11]), "+f"(d[12]), "+f"(d[13]), "+f"(d[14]), "+f"(d[15]), "+f"(d[16]), "+f"(d[17]), "+f"(d[18]), "+f"(d[19]), "+f"(d[20]), "+f"(d[21]), "+f"(d[22]), "+f"(d[23]), "+f"(d[24]), "+f"(d[25]), "+f"(d[26]), "+f"(d[27]), "+f"(d[28]), "+f"(d[29]), "+f"(d[30]), "+f"(d[31]), "+f"(d[32]), "+f"(d[33]), "+f"(d[34]), "+f"(d[35]), "+f"(d[36]), "+f"(d[37]), "+f"(d[38]), "+f"(d[39]), "+f"(d[40]), "+f"(d[41]), "+f"(d[42]), "+f"(d[43]), "+f"(d[44]), "+f"(d[45]), "+f"(d[46]), "+f"(d[47]), "+f"(d[48]), "+f"(d[49]), "+f"(d[50]), "+f"(d[51]), "+f"(d[52]), "+f"(d[53]), "+f"(d[54]), "+f"(d[55]), "+f"(d[56]), "+f"(d[57]), "+f"(d[58]), "+f"(d[59]), "+f"(d[60]), "+f"(d[61]), "+f"(d[62]), "+f"(d[63]), "+f"(d[64]), "+f"(d[65]), "+f"(d[66]), "+f"(d[67]), "+f"(d[68]), "+f"(d[69]), "+f"(d[70]), "+f"(d[71]), "+f"(d[72]), "+f"(d[73]), "+f"(d[74]), "+f"(d[75]), "+f"(d[76]), "+f"(d[77]), "+f"(d[78]), "+f"(d[79]), "+f"(d[80]), "+f"(d[81]), "+f"(d[82]), "+f"(d[83]), "+f"(d[84]), "+f"(d[85]), "+f"(d[86]), "+f"(d[87]), "+f"(d[88]), "+f"(d[89]), "+f"(d[90]), "+f"(d[91]), "+f"(d[92]), "+f"(d[93]), "+f"(d[94]), "+f"(d[95])
    : "l"(da), "l"(db), "r"(scale_d), "n"(TA), "n"(TB));
}

template<int TA, int TB>
__device__ __forceinline__ void wgmma_n48(float (&d)[24], uint64_t da, uint64_t db, int scale_d) {
  asm volatile("{\n.reg .pred p;\nsetp.ne.b32 p, %26, 0;\n"
    "wgmma.mma_async.sync.aligned.m64n48k16.f32.bf16.bf16 "
    "{%0, %1, %2, %3, %4, %5, %6, %7, %8, %9, %10, %11, %12, %13, %14, %15, %16, %17, %18, %19, %20, %21, %22, %23}, %24, %25, p, 1, 1, %27, %28;\n}\n"
    : "+f"(d[0]), "+f"(d[1]), "+f"(d[2]), "+f"(d[3]), "+f"(d[4]), "+f"(d[5]), "+f"(d[6]), "+f"(d[7]), "+f"(d[8]), "+f"(d[9]), "+f"(d[10]), "+f"(d[11]), "+f"(d[12]), "+f"(d[13]), "+f"(d[14]), "+f"(d[15]), "+f"(d[16]), "+f"(d[17]), "+f"(d[18]), "+f"(d[19]), "+f"(d[20]), "+f"(d[21]), "+f"(d[22]), "+f"(d[23])
    : "l"(da), "l"(db), "r"(scale_d), "n"(TA), "n"(TB));
}

__device__ __forceinline__ void wgmma_rs80(float (&d)[40], const uint4& a, uint64_t db, int scale_d) {
  asm volatile("{\n.reg .pred p;\nsetp.ne.b32 p, %45, 0;\n"
    "wgmma.mma_async.sync.aligned.m64n80k16.f32.bf16.bf16 {%0,%1,%2,%3,%4,%5,%6,%7,%8,%9,%10,%11,%12,%13,%14,%15,%16,%17,%18,%19,%20,%21,%22,%23,%24,%25,%26,%27,%28,%29,%30,%31,%32,%33,%34,%35,%36,%37,%38,%39}, {%40,%41,%42,%43}, %44, p, 1, 1, 1;\n}\n"
    : "+f"(d[0]), "+f"(d[1]), "+f"(d[2]), "+f"(d[3]), "+f"(d[4]), "+f"(d[5]), "+f"(d[6]), "+f"(d[7]), "+f"(d[8]), "+f"(d[9]), "+f"(d[10]), "+f"(d[11]), "+f"(d[12]), "+f"(d[13]), "+f"(d[14]), "+f"(d[15]), "+f"(d[16]), "+f"(d[17]), "+f"(d[18]), "+f"(d[19]), "+f"(d[20]), "+f"(d[21]), "+f"(d[22]), "+f"(d[23]), "+f"(d[24]), "+f"(d[25]), "+f"(d[26]), "+f"(d[27]), "+f"(d[28]), "+f"(d[29]), "+f"(d[30]), "+f"(d[31]), "+f"(d[32]), "+f"(d[33]), "+f"(d[34]), "+f"(d[35]), "+f"(d[36]), "+f"(d[37]), "+f"(d[38]), "+f"(d[39])
    : "r"(a.x), "r"(a.y), "r"(a.z), "r"(a.w), "l"(db), "r"(scale_d));
}

__device__ __forceinline__ void wgmma_ss80(float (&d)[40], uint64_t da, uint64_t db) {
  asm volatile("wgmma.mma_async.sync.aligned.m64n80k16.f32.bf16.bf16 {%0,%1,%2,%3,%4,%5,%6,%7,%8,%9,%10,%11,%12,%13,%14,%15,%16,%17,%18,%19,%20,%21,%22,%23,%24,%25,%26,%27,%28,%29,%30,%31,%32,%33,%34,%35,%36,%37,%38,%39}, %40, %41, 1, 1, 1, 0, 1;"
    : "+f"(d[0]), "+f"(d[1]), "+f"(d[2]), "+f"(d[3]), "+f"(d[4]), "+f"(d[5]), "+f"(d[6]), "+f"(d[7]), "+f"(d[8]), "+f"(d[9]), "+f"(d[10]), "+f"(d[11]), "+f"(d[12]), "+f"(d[13]), "+f"(d[14]), "+f"(d[15]), "+f"(d[16]), "+f"(d[17]), "+f"(d[18]), "+f"(d[19]), "+f"(d[20]), "+f"(d[21]), "+f"(d[22]), "+f"(d[23]), "+f"(d[24]), "+f"(d[25]), "+f"(d[26]), "+f"(d[27]), "+f"(d[28]), "+f"(d[29]), "+f"(d[30]), "+f"(d[31]), "+f"(d[32]), "+f"(d[33]), "+f"(d[34]), "+f"(d[35]), "+f"(d[36]), "+f"(d[37]), "+f"(d[38]), "+f"(d[39])
    : "l"(da), "l"(db));
}

__device__ const __align__(1024) uint32_t c_fft[11264] = {
0x2ddc2dba,0x2fe62eb5,0x2ed02eb5,0xafffaf6e,0x2e1f2dfe,0x2e3f2fbc,0x2f022ee9,0xad27af30,0x2e5e2e3f,0x1fd92b5e,0x2f302f1a,0x244ea875,0x2e992e7c,0xad96a993,0x2f5a2f46,0x2e992c32,
0xad00ad72,0xa17eac32,0xa17ea515,0xabb79cb6,0xac07ac87,0x2dfe29f1,0x1fd99648,0xafedae99,0xa9f1ab05,0x2fd42fbc,0x26a1244e,0xad96af91,0xa765a8d5,0x2aaa2e3f,0x29932875,0x2515a8d5,
0xae99adfe,0xb000aee9,0xaf6eafbc,0x2c872f30,0xaf80af1a,0xac32af02,0xae7caf02,0xaaaa217e,0xaff4afc9,0x2b5e9cb6,0xad27addc,0xaff4ae7c,0xafedb000,0x2ffc2eb5,0xab05ac5d,0xacd8af5a,
0x2c072d27,0x9fd92bb7,0xadfead00,0x2fed2e1f,0x25db2993,0xaf6eacb0,0xaf6eaed0,0x2c5d2f46,0xa5151648,0xaddcafdd,0xafffafd4,0xac321648,0xabb7a934,0x28d5a814,0xafa0afed,0xaff4af30,
0x2f302e3f,0x2fed2f1a,0x28142b5e,0x2934a875,0x30002fc9,0x26a12ddc,0xa5db1cb6,0x30002e7c,0x2f462fd4,0xaed0aa4e,0xacb0aa4e,0x29932e99,0x2d272e5e,0xae3faffc,0xaf02adfe,0xae1fa814,
0xa9f1acd8,0x26a1ab05,0x2fd42ffc,0xad96afed,0x2515a30e,0x2fff2e1f,0x2ddc2f1a,0x2c32a30e,0x2d272aaa,0x28752e7c,0x28752c32,0x2fa02f80,0x2f912e99,0xaee9a9f1,0xa8141648,0x9fd92c87,
0xafa0ae7c,0xafafaf46,0x2d002993,0xafa0ac32,0xaf91b000,0x244eac5d,0x2fbc2eb5,0xab05af5a,0xac87ae5e,0x30002dfe,0x2f6e2ffc,0x2e992814,0x1cb6a875,0x25152e1f,0x2c322e1f,0x2d722ff4,
0x27652c87,0xa9932a4e,0xaaaaadba,0xa5152c87,0xabb7a44e,0xafa0af30,0x28d59fd9,0xaff4ae5e,0xaf91ae1f,0x2814abb7,0x2ee92d00,0x1fd9ad27,0xaf5aafff,0x2fd42ed0,0x2fd42fe6,0x30002ddc,
0x2f462f6e,0x2c322fdd,0x2e7c2fdd,0xa993b000,0xab5e2934,0xafafacd8,0xad00244e,0x2f1a2dfe,0xaee9afaf,0x2f30a17e,0xadfeaff8,0xafbca30e,0x2c5da765,0xa9f12ddc,0x2d969cb6,0x2c5dacb0,
0x2bb7a993,0x2f1aa515,0x2f1a2765,0xaff4aaaa,0x2e5e2fd4,0xab052dba,0x29342f6e,0x2ee9a6a1,0xadba1fd9,0xa5dbafed,0xafddac07,0xaa4e2dfe,0xacb0aff8,0x2ddc2f02,0x9cb6ae3f,0xa765aff8,
0xaeb5af91,0xaa4eafed,0x9648ae5e,0xac5d2d4d,0x2ddca17e,0x2e7c2e3f,0x2fc92e3f,0x1cb6afa0,0x2bb72fe6,0xaff8a993,0xab5e2aaa,0x2bb72fc9,0xafbcaa4e,0x2f30a5db,0xadfeafdd,0xaee9adba,
0xacd828d5,0xaf91230e,0xaf30af02,0x2c072fa0,0xac5dafff,0x2dbaac32,0x2dbaa515,0xae99addc,0x2fc929f1,0xa9932eb5,0x2aaa2fdd,0x2fe629f1,0xa30e2dfe,0xa17eafed,0xaff8ac07,0xafaf1fd9,
0x2dfe2faf,0x28142ff8,0xae5e217e,0x2ffc230e,0xaf5aa515,0xac87af46,0xa6a1af80,0xaf5a2765,0x1cb6ae99,0x2e7c2dba,0x2fc92dba,0x2ddcac5d,0x2f1a2ee9,0xafafab05,0xad002934,0xab5e2e5e,
0x2dbaa814,0x2fdd9fd9,0x25db2f91,0x2a4eaee9,0x27652faf,0xaf4628d5,0xaf80ae1f,0xa5152faf,0xafa0addc,0x2e3fac32,0x2e3fa515,0xa17eafff,0x2dfea6a1,0xacd82dba,0x244e2f6e,0x29342fd4,
0xad27afc9,0xa30eafff,0x2faf2d72,0xad27ae7c,0x2ffc2a4e,0x28142fdd,0xae5e25db,0x2dfe2dba,0xac5d2c07,0xaa4eaf91,0x9648af30,0xaeb5acd8,0xa993aff4,0x2c322f1a,0x2e7c2f1a,0x2f462bb7,
0xae7c26a1,0xafff1648,0x2d72aa4e,0xafc926a1,0x230eaee9,0x2ff89fd9,0x217e2f91,0x2fafa814,0x2d4d2fa0,0xafed230e,0xae5eaf02,0xaf9128d5,0xb000aaaa,0x2fdda515,0x2fdd2765,0x2f6ea993,
0x9cb63000,0xacb02fd4,0xa7652fd4,0x2ddcaf5a,0x217eaffc,0x2ff4ac07,0x2875afbc,0xaff82934,0xa44e2ff4,0xadfea8d5,0xa9342fa0,0x2cd82bb7,0x25dbafe6,0x16482f46,0x29f1af80,0x25dbafc9,
0x2ff41cb6,0x2e1f2765,0x2e1f2cb0,0xa875addc,0xafbca5db,0x1fd9af5a,0xad4dad96,0xacd82fdd,0x2f5a2934,0xaeb52ee9,0x2c5d2e5e,0x3000ab05,0xaed0ab5e,0x2f80a30e,0xaaaaaf02,0xacb0ab5e,
0x25dbaffc,0x2d96afbc,0x2f5aac07,0xafdd2934,0xaaaa2fa0,0xafc92875,0xafe62875,0x29932d27,0x2d00aed0,0x28d52d72,0x2ff89cb6,0x2d00afe6,0xae5e2d96,0x2d4dafd4,0xaf91a6a1,0xafed29f1,
0xafbca17e,0xad4da875,0x1fd9aff4,0xacd82ff8,0x2e992aaa,0xaa4e2fe6,0xaa4e2fc9,0x2fd4a993,0xacb0ad96,0x2fffac87,0x2d72aeb5,0xa765ad96,0x28752f30,0xab5eac07,0xaf1a2cd8,0xae3f2f91,
0xa9342ff4,0xae5e2fa0,0xaee9a8d5,0x2b052bb7,0x2d96aed0,0x2eb59cb6,0x2c872d72,0x2d96afe6,0xaf802c5d,0x2765af6e,0xa515af6e,0xaf4625db,0x2ff8a44e,0xaff42d4d,0xa8752ffc,0xa17e2ee9,
0x2f5a244e,0x2c5d2934,0xaeb52dfe,0x3000acd8,0xacb0ad00,0x2d72aff8,0x2fffa8d5,0xa765ad00,0x217e2f80,0xaf022515,0xaf02a765,0xaf1a2f46,0x2b05afdd,0xa8142f5a,0x2c072d96,0x2d4d25db,
0x2b5eafe6,0x2f02af80,0x230e2f46,0x2b5eafc9,0xaf302d96,0xacd8a6a1,0x2c07afd4,0xaf9129f1,0x2fdda44e,0xad962ffc,0xaf5a2d4d,0xa5db2ee9,0xad72abb7,0x2e7ca17e,0x2fc9a17e,0x2fffad00,
0xaed0a5db,0xaaaaa9f1,0x2f809648,0xacb0a5db,0x28752e5e,0xaf1a2f91,0xab5ead4d,0xae3f2fed,0x2b05aff8,0x2c072875,0xa8142ff4,0x2d4d217e,0xaf6e2d72,0x2eb5afc9,0x2eb5ae7c,0x2dbaafff,
0xaf802f5a,0xafc92e99,0xafe62e99,0x2f46ad96,0x28d52b05,0xaf022fed,0x230e2cd8,0x2fa0affc,0x2fbcaf02,0xa9342d27,0x2ffcae1f,0x2c07ae3f,0xa6a1ac32,0x2a4e9cb6,0x9648ad72,0xa6a1a515,
0x28752aaa,0xa8d52cb0,0xa8d52ed0,0x2e3faf80,0x2fedaeb5,0x29349648,0x2f30aa4e,0x2814ac5d,0x1648ad4d,0x2e99acd8,0x2c87afbc,0xa9f11fd9,0xafe62d27,0x2fffafaf,0xaddc230e,0xaed02d27,
0x2fd4af30,0x2f6eae5e,0x2dbaa44e,0xa6a19fd9,0x1cb6ad27,0x2fe6aff4,0x2ed0aff4,0xad722b5e,0xafaf2cb0,0x2e1faf46,0xa8d5a993,0xafaf2ed0,0xac072f6e,0x2934ac87,0xaffc2e99,0xafbc3000,
0xa44eab5e,0x2b05ad00,0x2f91afaf,0xafbc2f1a,0xafd42d72,0x1648a765,0x1648acb0,0xafdd2fff,0xac322f5a,0xaaaa26a1,0xaf802c87,0xae7c2f5a,0x2d009fd9,0xae1f2cd8,0xad272fbc,0xabb72d4d,
0xaffc2f02,0xaee92e1f,0x244ead27,0xad4d2e3f,0xa9f12e7c,0xafdd2f80,0xaeb52aaa,0xa9f12c32,0x2d72a5db,0xafe63000,0xaed03000,0x9cb626a1,0x2fa0afbc,0xaf022f91,0x230e2b05,0x28d5a44e,
0x96482c07,0xac872d4d,0xae992b05,0x29f1a814,0x2ed0abb7,0xa9932b5e,0xaf462ff8,0x2cb0abb7,0x2f1aafff,0xa30e2765,0xa30e2cb0,0x2e1fad72,0x1fd9ac5d,0x244e9648,0x2e5eaa4e,0x2f30aeb5,
0x2ff8aed0,0x2e3faddc,0xaf022fff,0x2ff8afe6,0x2d4daf6e,0x2ee9ae99,0xa44e2c87,0x2ffcb000,0xa6a1a814,0x2f6eaf30,0x2dbaa934,0x2fd4afed,0xaf462d00,0x2fc9afa0,0x2fe6afa0,0x2f80afaf,
0x2515ac5d,0x2d72ad96,0x1cb629f1,0x2c32ac5d,0xad002814,0x2d27ad4d,0x2e1fab05,0x2bb7ac07,0xaffc2f1a,0x2cd8ad00,0x2fedafaf,0x2b05ab5e,0xadba2f80,0x2c87acb0,0x2c87aed0,0x2a4eaaaa,
0x2f802f6e,0x2fc92fdd,0x2fe62fdd,0xaf46b000,0x2fa02f91,0x2bb72e5e,0x2ff42fed,0xa8d5ad4d,0x2fbc2faf,0xa934217e,0x2ffc2ff8,0x2c07230e,0x2fd42fc9,0xaf5aad72,0x30002fff,0x2fd42e7c,
0x2bb72aaa,0x2f1a2cb0,0x2f1a2ed0,0xaff4af80,0x2cd82c5d,0x2f303000,0x2f912f5a,0xac07aeb5,0x2dba2d4d,0x25db2cd8,0x2fdd2fbc,0x2a4e9fd9,0x2e7c2e1f,0xad72a875,0x2fff2ff4,0x2fc92e1f,
0xa6a1a934,0x29f1a44e,0x2d962cd8,0xafd4adfe,0x1cb6a17e,0x2fe62e3f,0x2ed02e3f,0xad72afa0,0x28752515,0x2d272f80,0x2fa02f46,0x2875a765,0x2c072a4e,0xa93425db,0x2ffc2fdd,0x2fbc2dba,
0xae5eaf1a,0xa934ae3f,0x2b052875,0xaee9ab5e,0xac5dad72,0x2dba2765,0x2dba2cb0,0xae99afff,0xa765aa4e,0x2f802fd4,0x2f462e99,0x2515aa4e,0x230e9fd9,0x217e2cd8,0x2ff82fbc,0x2faf2d4d,
0xaffcafaf,0xaee9aff8,0x244ea17e,0xad4da30e,0xaf6eafe6,0x25dbaaaa,0x2c5d2993,0xaf6eafc9,0xad72ae99,0x2fe62dba,0x2ed02dba,0x1cb6ac5d,0xa8d5ac07,0x2bb72f30,0x2ff42f91,0x2fa02cd8,
0xadbaac07,0xafddad4d,0xa5dbab05,0xaa4e2814,0xafc9af02,0xaaaaaf1a,0x2993217e,0xafe6af02,0xafa0afff,0x2e3f2765,0x2e3f2cb0,0xa17ead72,0xad4daeb5,0x2e5e3000,0x2fed2f5a,0x2f912c5d,
0xa17e2765,0xad001cb6,0xabb7addc,0xa17e2cb0,0xad4daa4e,0xaee9afdd,0x244ea5db,0xaffcadba,0xafd4aee9,0x29f1a934,0x2d962b05,0xa6a1ae5e,0xaf46aff4,0x2fc92f1a,0x2fe62f1a,0x2f802bb7,
0x2cb02eb5,0x1cb62dba,0xaddcaf6e,0x27652eb5,0xa30e2814,0xaff8ad4d,0xa17eab05,0xafafac07,0xadfeab5e,0xa44eae3f,0x2cd82875,0xa934af1a,0xb000af80,0x2fdd2cb0,0x2fdd2ed0,0x2f6e2aaa,
0x2d723000,0x25152fd4,0x2c322fd4,0x1cb6af5a,0xae1f9fd9,0xae3faee9,0xaf02a814,0x2d272f91,0xacd8aff4,0x2ffc28d5,0xab05afa0,0xafedabb7,0x2e992515,0xad962aaa,0x2f5a2993,0x2e99a765,
0x2ff42ddc,0x2e1f2ed0,0x2e1f2fe6,0xa875afff,0xa8142c87,0xaffca9f1,0xadfe1648,0x2e5e2e99,0xaf5aaf30,0x2eb5a814,0xac5dafed,0xb000a934,0x2c32a8d5,0xa9932e3f,0x2f462875,0x2e7ca8d5,
0x2e991fd9,0x30002814,0x2f6e2ee9,0xac87af91,0x29932fa0,0xaed02875,0xacb02875,0x2f462d27,0xaff4ac32,0x2b5eaddc,0xad27afff,0xaff4a515,0x244ead96,0x1fd92fd4,0x2f3026a1,0x2e5ea9f1,
0x2814ad27,0x2dfeabb7,0x2ffc2d00,0xae5eae1f,0x2e992f80,0xaa4e2e7c,0xaa4e2c32,0x2fd42aaa,0xae7c1648,0x9cb6afdd,0xaddcafd4,0xafc91648,0xa875af91,0x2b5e2fbc,0x2f1a244e,0x2e3fab05,
0xab05aff4,0x244eafa0,0x2fbc28d5,0xaf91abb7,0x30002c32,0x26a12fff,0xa5db2ddc,0x30002515,0xaaaa2c5d,0xac32af6e,0xae7caf6e,0xaf8025db,0xad27afed,0x2e3f2dfe,0x2f021fd9,0x2e1fac07,
0xaf5aae5e,0xac5daf30,0x2eb59fd9,0xb000a44e,0x2e7ca30e,0x2ddc2e1f,0x1cb62f1a,0x2fc9a30e,0x217e2f46,0xaf02acb0,0xaf02aed0,0xaf1a2993,0xaf30ae99,0x2fbc29f1,0x2ee99648,0x2dfeac87,
0xafa0a515,0xafafa993,0x2d00aaaa,0xafa02765,0x2934ad96,0x2fed26a1,0x28142fd4,0x2f30a9f1,0x2c872fed,0xb0009fd9,0xaf6eadfe,0xae992c07,0xafffabb7,0x2fe6a17e,0x2ed0a17e,0x2ddcad00,
0xac322c87,0xaf462a4e,0x2993adba,0xae7c2c87,0xa875afed,0x2f1aab05,0x2b5e2ffc,0x2e3facd8,0x2f302e1f,0xaee92bb7,0xafbcad00,0xadfe2d27,0xaf6e9cb6,0x2eb5ac32,0x2eb5a515,0x2dbaad72,
0xaaaa2f5a,0xaed02e99,0xacb02e99,0x2f80ad96,0x2b5eaf30,0x2fafa44e,0x2d00ae5e,0xaf1a9fd9,0xac072f02,0xab05ad27,0xad4d2e1f,0x28142e3f,0x2c5daed0,0xa9f12fff,0x2d96addc,0x2c5dafe6,
0x28752f80,0xa8d52fe6,0xa8d52fc9,0x2e3faf46,0xa44eafd4,0x2f91adba,0x2b05af6e,0xafbc26a1,0x96482ffc,0xae99a44e,0xac872ee9,0x29f12d4d,0x2515aff8,0x1cb62f02,0x2d72ae3f,0x2c32aff8,
0x2eb52b05,0x2a4e2cd8,0x16482fed,0x2c5daffc,0xad72ad27,0x2cb0aff4,0x2765aff4,0xafff2b5e,0x2bb72e7c,0xaff82aaa,0xab5e2f80,0x2bb72c32,0xa814af6e,0x2b052c87,0x2d4dae99,0x2c07b000,
0x2feda8d5,0x2f30a30e,0x29342f02,0x2814afa0,0xafd49cb6,0x1648aed0,0x1648afe6,0xafdd2d72,0x2ed029f1,0xaf462eb5,0xa9932fdd,0x2cb029f1,0xad00ad4d,0x2e1f244e,0x2d27aee9,0x2bb7affc,
0x2d4daf02,0x2fbcae1f,0x2cd82d27,0x9fd9ae3f,0xaf5a2cb0,0xac87a993,0xa6a1af46,0xaf5a2ed0,0x2fffa5db,0xacb03000,0xa7653000,0x2d7226a1,0xaf1aa814,0x2fafa934,0x2d00af30,0x2b5eafed,
0x1648afbc,0x2c87affc,0x2e992934,0xa9f1ac07,0xac322faf,0xaf8028d5,0xaaaaae1f,0xae7c2faf,0x2f1aad72,0xa30e2ed0,0xa30e2fe6,0x2e1f1cb6,0xaffc26a1,0x2fedadba,0x2cd8af6e,0x2b05afd4,
0xad27ac32,0xa30ead72,0x2faf9cb6,0xad27a515,0x1fd92f6e,0xafbc2e99,0xacd8ac87,0xad4d3000,0x2c5dafbc,0x2a4e2b05,0x16482f91,0x2eb5a44e,0xaf802d00,0x2ed0afa0,0x2cb0afa0,0x2aaaafaf,
0xafe626a1,0xaddc1648,0x2fffaa4e,0xaed026a1,0x2d002c07,0xad272ffc,0xae1fa934,0xabb72fbc,0x1fd9afa0,0x2e5ea30e,0x244e2f02,0x2f30a8d5,0xadba2f46,0x2c87afe6,0x2c87afc9,0x2a4eaf80,
0xafff2d96,0xae7c2c5d,0xafc92c5d,0x2d72a9f1,0xa17e2dfe,0xaff42fbc,0xa8752ee9,0x2ff8af30,0x2fedad00,0xad4d2f1a,0x2f91ab5e,0x2e5eafaf,0x25dbae7c,0x16482993,0x29f1af46,0x25dbac32,
0xae3f2fff,0xaff82fc9,0xaff82e7c,0x2f02ad72,0x2c0725db,0xadfe2f5a,0x9fd92d96,0x2fedafdd,0x2f6eaf91,0xa6a12c07,0x2fd4acd8,0x2dbaaf30,0xa765ab5e,0x2aaaa30e,0x2993af02,0x2515ab5e,
0xa5db2dfe,0xad962ee9,0xaf5a2fbc,0x2fddaf30,0x2f46ab5e,0xa7652bb7,0x25152bb7,0x2f80aff8,0x2d00afc9,0x28d59cb6,0x2ff8addc,0x2d00ae7c,0xacd89648,0x2dfeac5d,0x2934aeb5,0x244eaa4e,
0x2c07217e,0x9fd92875,0xadfe2ff4,0x2fedaff8,0x2fddaf46,0x29f1a515,0x29f12765,0x2eb5af80,0x2515ad96,0x2ddcac87,0x2fffaeb5,0x2c32ad96,0xaf022b05,0x2fa0aee9,0x28d5ae5e,0x230ea934,
0x2f91ad00,0x2cd8ab5e,0xac072f1a,0x2f30afaf,0x2d96afc9,0x2eb5addc,0x2c879cb6,0x2d96ae7c,0xa993a6a1,0x2fc9af5a,0x2fe6af5a,0x2aaaac87,0xaff82e5e,0x2ff4affc,0x2875adfe,0x217ea814,
0x2f6eafed,0x2fd4af91,0xa6a12d4d,0x2dbaae5e,0x2515ad00,0x2fffaff8,0x2ddca8d5,0x2c32ad00,0xae1f2993,0x2fafafe6,0x2fafafc9,0x28d5aaaa,0xaf912fdd,0x2ee9af5a,0x2814ad96,0x1fd9a5db,
0x2b5eae7c,0x2f02af46,0x230e2993,0x2b5eac32,0xab059648,0x2e5eaeb5,0x2ee9ac5d,0x2934aa4e,0xafdd2e5e,0x2d96adfe,0x2f5aaffc,0x25dba814,0xaddc2faf,0x2cb0ad27,0x2765ad27,0x1cb6a30e,
0xa765a5db,0x2993a9f1,0x2aaa9648,0x2515a5db,0xaf022cd8,0x28d5a934,0x2fa0adfe,0x230ea44e,0xaf912ff8,0x2814a875,0x2ee9aff4,0x1fd9a17e,0xaa4e2ddc,0x26a1a765,0x26a1acb0,0x16489cb6,
0x2d722d96,0x25152c5d,0x2c322c5d,0x1cb6a9f1,0x2d272d4d,0xad00a814,0x2bb72c07,0x2e1f2b05,0x2cd82d00,0xaffcaf1a,0x2b052b5e,0x2fed2faf,0x2c872cb0,0xadbaaf80,0x2a4e2aaa,0x2c872ed0,
0x2e3f2ddc,0x2ff82ed0,0x2ff82fe6,0xaf02afff,0x2ee92e99,0x2d4d2f6e,0x2ffc3000,0xa44eac87,0x2f6e2f30,0xa6a12814,0x2fd42fed,0x2dba2934,0x2fc92fa0,0xaf46ad00,0x2f802faf,0x2fe62fa0,
0xac87ad4d,0x9648ac07,0x29f12814,0xae99ab05,0xa993ab5e,0x2ed02bb7,0x2cb02bb7,0xaf46aff8,0xa30ea765,0x2f1a2fff,0x2e1f2d72,0xa30eacb0,0x244e1648,0x1fd92c5d,0x2f302eb5,0x2e5e2a4e,
0xaee9ae1f,0xaffcaf02,0xad4dae3f,0x244e2d27,0xafddaf80,0xa9f1ae7c,0xa9f1ac32,0xaeb5aaaa,0xafe6b000,0x2d7225db,0x9cb6a6a1,0xaed0b000,0xaf02af91,0x2fa02fbc,0x28d5244e,0x230eab05,
0x2b052d00,0xa44e2b5e,0xafbcaf1a,0x2f912faf,0x16482765,0xafd4ad72,0xafddafff,0x16482cb0,0xaaaaa6a1,0xac32af5a,0xae7caf5a,0xaf80ac87,0xae1facd8,0x2d001fd9,0xabb7ad4d,0xad27afbc,
0x2f6e2e5e,0x2fd42f30,0xa6a11fd9,0x2dba244e,0x2fe62ff4,0x1cb62d27,0xad72ab5e,0x2ed02ff4,0x2e1f2f46,0xafafacb0,0xafafaed0,0xa8d52993,0x29342c87,0xac07af6e,0xafbcb000,0xaffcae99,
0xa8d5acb0,0x2875aaaa,0x2e3f2f80,0xa8d5aed0,0x29341648,0x2fed2eb5,0x28142c5d,0x2f302a4e,0x2e992cd8,0x16482d4d,0xa9f19fd9,0x2c872fbc,0x2fff2faf,0xafe6ad27,0xaed0ad27,0xaddca30e,
0xafc9ae99,0xaf80af5a,0x2f462d96,0xafe6ae99,0xaf02afed,0x28d5ab05,0x2fa02ffc,0x230eacd8,0xa934ad27,0x2fbc2f02,0x2c072e3f,0x2ffc2e1f,0x2a4e1cb6,0xa6a12c32,0xa6a12515,0x96482d72,
0xaaaa29f1,0xaed025db,0xacb025db,0x2f801648,0xaf1aaf91,0x2875ae5e,0xae3fafed,0xab5e2d4d,0x2c07a875,0x2b052ff8,0x2d4da17e,0xa814aff4,0x2eb52fc9,0xaf6ead72,0x2dba2fff,0x2eb52e7c,
0x2f022f80,0x2b5e2fe6,0x2b5e2fc9,0x230eaf46,0xacd826a1,0xaf30ad96,0xaf91a9f1,0x2c072fd4,0xad96affc,0x2fdd244e,0xa5dbaee9,0xaf5aad4d,0x2e7c217e,0xad722bb7,0x2fff2d00,0x2fc9217e,
0x2c5da934,0x2f5aa44e,0x30002cd8,0xaeb5adfe,0x2d722ff8,0xacb02d00,0xa7652d00,0x2fff28d5,0xaf02a515,0x217eaf80,0xaf1aaf46,0xaf022765,0xa814af5a,0x2b052fdd,0x2d4da5db,0x2c07ad96,
0xae5eafa0,0xa934aff4,0x2b05abb7,0xaee928d5,0x2eb51cb6,0x2d962ed0,0x2d962fe6,0x2c87ad72,0x27652f6e,0xaf80ac5d,0xaf46a5db,0xa5152f6e,0xaff4ad4d,0x2ff8244e,0xa17eaee9,0xa875affc,
0xad4d2875,0xafbc217e,0xacd8aff8,0x1fd92ff4,0xaa4eafe6,0x2e99aaaa,0x2fd42993,0xaa4eafc9,0x2fff2c87,0xacb02d96,0xa7652d96,0x2d722eb5,0xab5e2c07,0x2875af30,0xae3faf91,0xaf1aacd8,
0x2d962fbc,0x25db2ffc,0xafdda934,0x2f5a2c07,0xafc9a875,0xaaaaafa0,0x2993ad27,0xafe6a875,0x28d5ad72,0x2d002ed0,0x2d002fe6,0x2ff81cb6,0x2d4d2fd4,0xae5ead96,0xafeda9f1,0xaf9126a1,
0x2e1fa765,0x2ff49cb6,0xa8752ddc,0x2e1facb0,0x1fd92f5a,0xafbc25db,0xacd8afdd,0xad4d2d96,0xaeb5aee9,0x2f5aa934,0x30002b05,0x2c5dae5e,0x2f80230e,0xaed02b5e,0xacb02b5e,0xaaaa2f02,
0xacb0afd4,0x9cb6b000,0x2ddc2f5a,0xa765afd4,0x2ff42c07,0x217e2ffc,0xaff8a934,0x28752fbc,0xadfe28d5,0xa44eaff4,0x2cd8abb7,0xa934afa0,0x1648af46,0x25db2fe6,0x25db2fc9,0x29f12f80,
0xafff9648,0xae7ca6a1,0xafc9a6a1,0x2d722a4e,0x2ff81fd9,0x230e2ee9,0x2faf2814,0x217eaf91,0xafeda30e,0x2d4dafa0,0xaf91a8d5,0xae5e2f02,0x2fdd2515,0xb0002aaa,0x2f6e2993,0x2fdda765,
0xa30e2fff,0xad272fc9,0xad272e7c,0x2fafad72,0x2814afdd,0x2ffcaa4e,0x2dfeadba,0xae5ea5db,0xaa4e2f91,0xac5dac07,0xaeb52cd8,0x96482f30,0x2c32af1a,0xa9932ff4,0x2f46abb7,0x2e7caf1a,
0x2fdd1fd9,0x2dba2814,0x2a4e2ee9,0x25dbaf91,0xaf46a8d5,0x2765afaf,0xa515afaf,0xaf802e1f,0x2e3f2c32,0xafa02ddc,0xa17e2fff,0x2e3f2515,0xacd8adba,0x2dfe26a1,0x2934afd4,0x244eaf6e,
0x2814aff8,0x2dfeafaf,0x2ffca30e,0xae5ea17e,0xac872f46,0xaf5a2515,0xaf5aa765,0xa6a12f80,0x2e7cadba,0x1cb62e99,0x2ddc2c5d,0x2fc9adba,0xafaf2b05,0x2f1aaee9,0xab5eae5e,0xad00a934,
0xaf91a30e,0xacd8a8d5,0x2c07afa0,0xaf302f02,0x2dba2c32,0xac5d2fff,0xae992ddc,0x2dba2515,0xa993aeb5,0x2fc9a9f1,0x2fe6a9f1,0x2aaaafdd,0xa17e2fed,0xa30eadfe,0xafaf9fd9,0xaff82c07,
0xaa4e2fed,0xaeb52f91,0xac5dad4d,0x96482e5e,0x2e7cae3f,0x2ddc217e,0x1cb62fa0,0x2fc9ae3f,0xaff82993,0x2bb7afe6,0x2bb7afc9,0xab5eaaaa,0x2f3025db,0xafbc2a4e,0xaee92dba,0xadfe2fdd,
0x2f1a2515,0x2bb72993,0xaff42aaa,0x2f1aa765,0xab05adba,0x2e5eafd4,0x2ee926a1,0x2934af6e,0xa5db2fed,0xadba9fd9,0xaa4eadfe,0xafdd2c07,0x2ddcaf02,0xacb02ff8,0xa7652ff8,0x9cb62e3f,
0x2c32afdd,0x2f46af6e,0xa9933000,0x2e7cafdd,0xafaf2cd8,0xab5ea934,0x2f1aadfe,0xad00a44e,0x2f30217e,0xaee92faf,0xafbc230e,0xadfe2ff8,0xa9f1addc,0x2c5d2765,0x2c5d2cb0,0x2d961cb6,
0xa993aa4e,0x2765ac87,0xa515ac87,0xaaaa2dba,0xafa02f30,0xabb7244e,0xaff42e5e,0x28d51fd9,0x28142bb7,0xaf912e1f,0x1fd92d27,0x2ee9ad00,0x2fd4aed0,0xaf5a2fff,0x3000addc,0x2fd4afe6,
0xafaf2f46,0xafa02e7c,0xafa02c32,0x2d00a993,0x244e2c5d,0xaf913000,0xab052f5a,0x2fbcaeb5,0x3000adfe,0xac872e5e,0x2e99a814,0x2f6eaffc,0x2515ae1f,0x1cb62875,0x2d72aff4,0x2c32ae1f,
0x26a12b05,0xa9f12cd8,0xad962fed,0x2fd4affc,0x2fffae1f,0x2515230e,0x2c32230e,0x2ddcaf1a,0x2875ae7c,0x2d27aaaa,0x2fa0af80,0x2875ac32,0xaee929f1,0x2f91ae99,0x9fd9ac87,0xa8149648,
0x2fedaf1a,0x2f30ae3f,0x29342875,0x2814ab5e,0x26a1addc,0x3000afc9,0x3000ae7c,0xa5db9cb6,0xaed02a4e,0x2f46afd4,0x2993ae99,0xacb02a4e,0xae3f2ffc,0x2d27ae5e,0xae1f2814,0xaf022dfe,
0x9fd9abb7,0x2c07ad27,0x2fedae1f,0xadfe2d00,0xaf6e2cb0,0x25dba993,0x2c5daf46,0xaf6e2ed0,0xaddc2fdd,0xa5159648,0xac329648,0xafff2fd4,0x28d52814,0xabb72934,0xaff42f30,0xafa02fed,
0xb0002ee9,0xae992dfe,0x2c87af30,0xaf6e2fbc,0xac322f02,0xaf802f1a,0xaaaaa17e,0xae7c2f02,0x2b5e1cb6,0xaff42fc9,0xaff42e7c,0xad272ddc,0x2ffcaeb5,0xafed3000,0xacd82f5a,0xab052c5d,
0xa17e2c32,0xad002d72,0xabb71cb6,0xa17e2515,0x2dfea9f1,0xac072c87,0xafed2e99,0x1fd91648,0x2fd4afbc,0xa9f12b05,0xad962f91,0x26a1a44e,0x2aaaae3f,0xa76528d5,0x251528d5,0x2993a875,
0x2fe6aeb5,0x2ddcadba,0xafff2f6e,0x2ed0aeb5,0x2e3fafbc,0x2e1fadfe,0xad272f30,0x2f02aee9,0x1fd9ab5e,0x2e5eae3f,0x244e2875,0x2f30af1a,0xad962993,0x2e99ae7c,0x2e99ac32,0x2f5aaf46,
0x299329f1,0xa76525db,0x251525db,0x2aaa1648,0x28d52934,0xaf02acd8,0x230e244e,0x2fa02dfe,0x28142875,0xaf91aff8,0x1fd9217e,0x2ee92ff4,0x26a12765,0xaa4eaddc,0x16481cb6,0x26a12cb0,
0x2f022f46,0x2b5e2e7c,0x2b5e2c32,0x230ea993,0x2e5e2eb5,0xab051648,0x29342a4e,0x2ee92c5d,0x2d962dfe,0xafddae5e,0x25db2814,0x2f5a2ffc,0x2cb02d27,0xaddcafaf,0x1cb6230e,0x27652d27,
0x2fd42f91,0x2f6e2fed,0x2dba2e5e,0xa6a1ad4d,0x2fff2ff8,0x25152d00,0x2c322d00,0x2ddc28d5,0x2faf2fe6,0xae1fa993,0x28d52aaa,0x2faf2fc9,0x2ee92f5a,0xaf91afdd,0x1fd925db,0x28142d96,
0x2cd82b5e,0x2f912d00,0x2f302faf,0xac07af1a,0x2eb52ddc,0x2d962fc9,0x2d962e7c,0x2c871cb6,0x2fc92f5a,0xa99326a1,0x2aaa2c87,0x2fe62f5a,0x2ff42ffc,0xaff8ae5e,0x217e2814,0x28752dfe,
0x9fd9a875,0x2c07a17e,0x2fed2ff8,0xadfeaff4,0x29f12515,0x2fdd2f46,0x2eb52f80,0x29f1a765,0x2ddc2c87,0x25152d96,0x2c322d96,0x2fff2eb5,0x2fa02ee9,0xaf02ab05,0x230e2934,0x28d52e5e,
0xad96aee9,0xa5dbadfe,0x2fdd2f30,0xaf5aafbc,0xa765abb7,0x2f462b5e,0x2f802ff8,0x2515abb7,0x28d51cb6,0x2d002fc9,0x2d002e7c,0x2ff82ddc,0x2dfe2c5d,0xacd81648,0x244e2a4e,0x29342eb5,
0xaff8afc9,0xae3fafff,0x2f022d72,0xaff8ae7c,0xadfeaf5a,0x2c07a5db,0x2fed2fdd,0x9fd9ad96,0xa6a1ac07,0x2f6e2f91,0x2dba2f30,0x2fd42cd8,0x2aaa230e,0xa7652b5e,0x25152b5e,0x29932f02,
0xae7cac5d,0xafffad96,0x2d7229f1,0xafc9ac5d,0xaff4afbc,0xa17eadfe,0x2ff82f30,0xa875aee9,0xad4daf1a,0x2fed2d00,0x2e5e2faf,0x2f912b5e,0x1648a993,0x25db2e7c,0x25db2c32,0x29f12f46,
0xaddc9648,0xafe6a6a1,0xaed0a6a1,0x2fff2a4e,0xad27affc,0x2d00ac07,0xabb7afbc,0xae1f2934,0x2e5e230e,0x1fd92fa0,0x2f3028d5,0x244eaf02,0x2c872fe6,0xadbaaf46,0x2a4e2f80,0x2c872fc9,
0xa30e2d72,0xad272c32,0xad272515,0x2faf1cb6,0xafbcae99,0x1fd9af6e,0xad4db000,0xacd82c87,0x2a4eab05,0x2c5d2fbc,0x2eb5244e,0x1648af91,0x2ed02fa0,0xaf80ad00,0x2aaa2faf,0x2cb02fa0,
0x2c872ffc,0x16482fbc,0xa9f12c07,0x2e99a934,0xaf80a8d5,0xac32afaf,0xae7cafaf,0xaaaa2e1f,0xa30eaed0,0x2f1a2d72,0x2e1f9cb6,0xa30eafe6,0x2fed2dba,0xaffca6a1,0x2b052fd4,0x2cd82f6e,
0x2fbc2e1f,0x2d4d2f02,0x9fd92e3f,0x2cd8ad27,0xac872993,0xaf5aacb0,0xaf5aaed0,0xa6a12f46,0xacb0b000,0x2fff25db,0x2d72a6a1,0xa765b000,0x2faf2934,0xaf1a2814,0x2b5e2fed,0x2d002f30,
0x2f30230e,0x2fed28d5,0x28142fa0,0x2934af02,0x16482ed0,0xafd41cb6,0xafddad72,0x16482fe6,0xaf46aeb5,0x2ed0a9f1,0x2cb0a9f1,0xa993afdd,0x2e1fa44e,0xad002d4d,0x2bb72ffc,0x2d272ee9,
0x2a4eacd8,0x2eb5ab05,0x2c5d2ffc,0x1648afed,0x2cb02ff4,0xad722d27,0xafffab5e,0x27652ff4,0xaff8aaaa,0x2bb7ae7c,0x2bb7ac32,0xab5eaf80,0x2b05ac87,0xa8142f6e,0x2c073000,0x2d4d2e99,
0xa8d5afe6,0x2875af80,0x2e3f2f46,0xa8d5afc9,0x2f912dba,0xa44e2fd4,0xafbca6a1,0x2b052f6e,0xae99244e,0x9648affc,0x29f1ad4d,0xac87aee9,0x1cb6af02,0x25152ff8,0x2c322ff8,0x2d722e3f,
0xaed0ae99,0xaaaaaf5a,0x2f802d96,0xacb0ae99,0x2faf244e,0x2b5e2f30,0xaf1a1fd9,0x2d002e5e,0xab052d27,0xac07af02,0x2814ae3f,0xad4dae1f,0xa9f1afff,0x2c5d2ed0,0x2c5d2fe6,0x2d962ddc,
0xaf46aa4e,0xac32ac87,0xae7cac87,0x29932dba,0x2f1a2b05,0xa8752fed,0x2e3f2cd8,0x2b5eaffc,0xaee9abb7,0x2f30ae1f,0xadfead27,0xafbc2d00,0x2eb52c32,0xaf6e1cb6,0x2dba2d72,0x2eb52515,
0xafaf2993,0xafa02515,0xafa0a765,0x2d002aaa,0x2feda6a1,0x29342d96,0x2f3029f1,0x2814afd4,0xb0001fd9,0x2c87afed,0xae99ac07,0xaf6e2dfe,0x2fe6217e,0xafff2bb7,0x2ddc2d00,0x2ed0217e,
0xac5d2f30,0xaf5a2e5e,0xb000244e,0x2eb51fd9,0x2ddcae1f,0x2e7c230e,0x2fc9230e,0x1cb6af1a,0xaf022cb0,0x217eaf46,0xaf1aa993,0xaf022ed0,0x2fbca9f1,0xaf302e99,0x2dfe2c87,0x2ee91648,
0x244e2fa0,0xab052ff4,0xaf912bb7,0x2fbca8d5,0x26a1afff,0x3000ac32,0x3000a515,0xa5dbaddc,0xac322f6e,0xaaaaac5d,0xaf80a5db,0xae7c2f6e,0x2e3fadfe,0xad272fed,0x2e1f2c07,0x2f029fd9,
0x2dfe2bb7,0x28142d27,0xae5e2e1f,0x2ffcad00,0xaa4eae7c,0x2e99af80,0x2fd4aaaa,0xaa4eac32,0x9cb62fdd,0xae7c9648,0xafc99648,0xaddc2fd4,0x2b5eafbc,0xa8752f91,0x2e3f2b05,0x2f1aa44e,
0x3000a814,0x2e999fd9,0xac872f91,0x2f6eaee9,0xaed0a875,0x2993afa0,0x2f46ad27,0xacb0a875,0x2b5e2ddc,0xaff42c32,0xaff42515,0xad272fff,0x1fd9afd4,0x244e2d96,0x2e5e29f1,0x2f30a6a1,
0x2e1faed0,0x2ff4addc,0xa8752fff,0x2e1fafe6,0xaffc29f1,0xa814ac87,0x2e5eae99,0xadfe9648,0x2eb52814,0xaf5a2f30,0xb0002934,0xac5d2fed,0xa993ae3f,0x2c3228d5,0x2e7c28d5,0x2f46a875,
0x2515afd4,0x2d72b000,0x1cb62f5a,0x2c32afd4,0xae3f2ee9,0xae1f1fd9,0x2d27af91,0xaf022814,0x2ffca8d5,0xacd82ff4,0xafed2bb7,0xab052fa0,0xad96aaaa,0x2e99a515,0x2e992765,0x2f5aa993,
0x1cb6adba,0x2cb0aeb5,0x2765aeb5,0xaddc2f6e,0xaff82d4d,0xa30ea814,0xafaf2c07,0xa17e2b05,0xa44e2e3f,0xadfe2b5e,0xa9342f1a,0x2cd8a875,0x2fddacb0,0xb0002f80,0x2f6eaaaa,0x2fddaed0,
0xad009cb6,0xa17ea765,0xa17eacb0,0xabb72ddc,0xaee92fdd,0xad4d2a4e,0xaffc2dba,0x244e25db,0x29f12934,0xafd42ee9,0xa6a12e5e,0x2d96ab05,0x2fc9af1a,0xaf462ff4,0x2f80abb7,0x2fe6af1a,
0xafdd2d4d,0xadba2c07,0xaa4ea814,0xa5db2b05,0xaaaa2f1a,0xafc92f02,0xafe62f02,0x2993a17e,0x2e3fa765,0xafa02fff,0xa17e2d72,0x2e3facb0,0x2e5eb000,0xad4d2eb5,0x2f91ac5d,0x2fedaf5a,
0xaee92ff8,0xaffc2faf,0xad4d230e,0x244e217e,0x25db2aaa,0xaf6e2fe6,0xaf6e2fc9,0x2c5da993,0x2fe6adba,0xad722e99,0x1cb62c5d,0x2ed0adba,0x2bb7af30,0xa8d52c07,0x2fa0acd8,0x2ff4af91,
0xa9342e3f,0xae5e2f1a,0xaee92b5e,0x2b05a875,0x2dbaa765,0xac5d2d72,0xae992fff,0x2dbaacb0,0x2f80afd4,0xa7652a4e,0x25152a4e,0x2f46ae99,0x217eacd8,0x230e1fd9,0x2fafad4d,0x2ff8afbc,
0x29f1244e,0xa6a12934,0xafd42dfe,0x2d96acd8,0x2fe6ae3f,0x1cb6217e,0xad722fa0,0x2ed0ae3f,0x2d27af80,0x2875a515,0x28752765,0x2fa0af46,0xa934a5db,0x2c07aa4e,0x2fbcadba,0x2ffcafdd,
0x2f1aacb0,0x2bb7aaaa,0xaff42f80,0x2f1aaed0,0x2f30b000,0x2cd8ac5d,0xac072eb5,0x2f91af5a,0x25dbacd8,0x2dbaad4d,0x2a4e1fd9,0x2fddafbc,0xad722875,0x2e7cae1f,0x2fc9ae1f,0x2fffaff4,
0x2fc9afdd,0x2f80af6e,0xaf463000,0x2fe6afdd,0x2bb7ae5e,0x2fa0af91,0xa8d52d4d,0x2ff4afed,0xa934a17e,0x2fbcafaf,0x2c07a30e,0x2ffcaff8,0xaf5a2d72,0x2fd4afc9,0x2fd4ae7c,0x3000afff,
0x9d4d9e16,0xada6ae7d,0x9b769c84,0xabf0accf,0x985299e4,0xa897aa43,0x90b6957f,0xa102a5d8,0x13db0a48,0x242c1aad,0x191b1712,0x296d2783,0x1c201aad,0x2c632b1a,0x1db21ce9,0x2e112d3a,
0xa3f4a491,0xae51af42,0xa199a2c6,0xac70ad60,0x9e7ba06b,0xa922ab00,0x97129c20,0xa199a688,0x19e410b6,0x24aa1b76,0x1fa81d4d,0x2a112833,0x222f2102,0x2ce82bf0,0x2445235d,0x2ec92dd8,
0xa6a1a79c,0xaefcb004,0xa4aaa5a5,0xace8adf2,0xa166a35d,0xa9acabbe,0x99e49edf,0xa22fa738,0x1ce913db,0x25281c20,0x2262206b,0x2ab528a4,0x2528242c,0x2d6d2c63,0x271f2623,0x2f822e77,
0xa8a4a954,0xafa8b067,0xa688a7e8,0xad60ae84,0xa38fa528,0xaa37ac3d,0x9c20a0d0,0xa2c6a7e8,0x1edf157f,0x25a51c84,0x2478222f,0x2b592915,0x273825d8,0x2df22ccf,0x28fc284c,0x301d2f16,
0xa9f8aadb,0xb02ab0ca,0xa833a915,0xadd8af16,0xa4dca6a1,0xaac1ac9c,0x9d4da22f,0xa35da84c,0x206b1712,0x26231ce9,0x25bf23f4,0x2bfd2987,0x28a42783,0x2e772d3a,0x2a692987,0x307a2fb5,
0xab4cac31,0xb081b12e,0xa922aa37,0xae51afa8,0xa5f1a80d,0xab4cacfb,0x9e7ba38f,0xa3f4a8a4,0x21661852,0x26a11d4d,0x270524dc,0x2c5029f8,0x29ac2897,0x2efc2da6,0x2bd72ac1,0x30d7302a,
0xac50acf5,0xb0d7b192,0xaa11ab59,0xaec9b01d,0xa705a8ca,0xabd7ad5a,0x9fa8a478,0xa445a8fc,0x2262191b,0x271f1db2,0x282625bf,0x2ca22a69,0x2ab5296d,0x2f822e11,0x2ca22bfd,0x3135307a,
0xacfbadb9,0xb12eb1f7,0xab00ac3d,0xaf42b067,0xa80da987,0xac31adb9,0xa06ba528,0xa491a954,0x235d19e4,0x279c1e16,0x28ca26a1,0x2cf52adb,0x2bbe2a43,0x30042e7d,0x2d5a2c9c,0x319230ca,
0xb185b25c,0xb426b4cc,0xafbbb0b1,0xb1c6b306,0xac76ae18,0xaea3b08a,0xa4dca9ac,0xa738ac37,0x280d1e7b,0x2a0520d0,0x2d472b4c,0x2fdb2d6d,0x30472ee9,0x32663128,0x31f0311b,0x347933a8,
0xb1ddb2c1,0xb453b501,0xb01ab0fb,0xb204b352,0xacbcae77,0xaee9b0ba,0xa528aa05,0xa783ac63,0x284c1edf,0x2a432102,0x2d992bbe,0x30172da6,0x308a2f55,0x32aa315f,0x324f316b,0x34aa33fc,
0xb235b327,0xb481b537,0xb057b145,0xb242b39e,0xad01aed6,0xaf2fb0eb,0xa573aa5d,0xa7cfac90,0x288b1f44,0x2a822134,0x2deb2c18,0x30412ddf,0x30ce2fc2,0x32ef3196,0x32ae31bc,0x34db3428,
0xb28db38e,0xb4afb56d,0xb094b18f,0xb280b3eb,0xad47af36,0xaf75b11b,0xa5bfaab5,0xa80dacbc,0x28ca1fa8,0x2ac12166,0x2e3e2c50,0x306a2e18,0x31113017,0x333531cd,0x330d320e,0x350d3452,
0xb2e5b3f5,0xb4ddb5a3,0xb0d1b1da,0xb2beb41c,0xad8caf95,0xafbbb14b,0xa60aab0d,0xa833ace8,0x29092006,0x2b002199,0x2e902c89,0x30942e51,0x3155304d,0x337a3204,0x336d325f,0x3540347c,
0xb33eb42e,0xb50cb5da,0xb10eb224,0xb2fcb443,0xadd2aff5,0xb001b17c,0xa655ab65,0xa859ad14,0x29482039,0x2b4021cb,0x2ee32cc2,0x30be2e8a,0x31993084,0x33c0323b,0x33cd32b1,0x357234a6,
0xb398b463,0xb53ab612,0xb14bb26f,0xb33bb469,0xae18b02a,0xb024b1ac,0xa6a1abbe,0xa87ead40,0x2987206b,0x2b7f21fd,0x2f362cfb,0x30e72ec3,0x31dd30ba,0x34033273,0x34173303,0x35a534d1,
0xb3f2b497,0xb569b64a,0xb189b2bb,0xb37ab490,0xae5eb05a,0xb047b1dd,0xa6ecac0b,0xa8a4ad6d,0x29c6209d,0x2bbe222f,0x2f882d34,0x31112efc,0x322130f1,0x342632aa,0x34483356,0x35d934fc,
0xb599b682,0xb722b82e,0xb3b9b4b7,0xb4ddb5f9,0xb06ab20e,0xb185b398,0xa8caad99,0xa9f8aefc,0x2bfd2262,0x2cfb23f4,0x313b2f36,0x328d3081,0x344932e2,0x35693453,0x360d3527,0x37bd368b,
0xb5c9b6bb,0xb755b84d,0xb3f8b4df,0xb4feb622,0xb08db23e,0xb1a9b3ca,0xa8f0adc5,0xaa1eaf29,0x2c1e2294,0x2d1b2413,0x31652f6f,0x32b7309d,0x346d331a,0x358e3470,0x36413553,0x37f536ba,
0xb5f9b6f5,0xb789b86d,0xb41cb506,0xb51fb64c,0xb0b1b26f,0xb1cdb3fc,0xa915adf2,0xaa43af55,0x2c3d22c6,0x2d3a242c,0x318f2fa8,0x32e230ba,0x34903352,0x35b3348d,0x3676357e,0x381736e8,
0xb629b72f,0xb7bdb88d,0xb43cb52e,0xb540b676,0xb0d4b2a1,0xb1f0b417,0xa93bae1e,0xaa69af82,0x2c5d22f9,0x2d5a2445,0x31b92fe2,0x330d30d7,0x34b4338b,0x35d934aa,0x36ab35ab,0x38343717,
0xb65ab76a,0xb7f1b8ad,0xb45cb556,0xb561b6a0,0xb0f7b2d2,0xb214b430,0xa961ae4b,0xaa8fafaf,0x2c7d232b,0x2d79245f,0x31e3300e,0x333830f4,0x34d833c3,0x35fe34c7,0x36e035d7,0x38513746,
0xb68bb7a5,0xb813b8ce,0xb47cb57e,0xb582b6ca,0xb11bb303,0xb238b449,0xa987ae77,0xaab5afdb,0x2c9c235d,0x2d992478,0x320e302a,0x33633111,0x34fc33fc,0x362434e4,0x37173604,0x386f3775,
0xb6bdb7e2,0xb82eb8f0,0xb49cb5a7,0xb5a3b6f5,0xb13eb335,0xb25cb463,0xa9acaea3,0xaadbb004,0x2cbc238f,0x2db92491,0x32383047,0x338e312e,0x3520341a,0x364a3501,0x374d3631,0x388d37a5,
0xb6efb80f,0xb849b911,0xb4bdb5d0,0xb5c5b720,0xb162b366,0xb280b47c,0xa9d2aed0,0xab00b01a,0x2cdb23c2,0x2dd824aa,0x32623064,0x33b9314b,0x35453437,0x3670351f,0x3785365e,0x38ab37d6,
0xb865b934,0xb94dba5c,0xb5e7b74c,0xb6fcb85a,0xb2a4b495,0xb3c6b564,0xab26b031,0xac2bb0e4,0x2df824c3,0x2ef6258c,0x33e43168,0x34a13252,0x3697353c,0x37d4362d,0x38ca3803,0x39d038d0,
0xb880b957,0xb96bba84,0xb609b777,0xb720b872,0xb2c8b4af,0xb3ebb57e,0xab4cb047,0xac3db0fb,0x2e1824dc,0x2f1625a5,0x34083185,0x34b7326f,0x36bd355a,0x37fd364c,0x38e9381c,0x39f338eb,
0xb89cb97a,0xb98abaad,0xb62bb7a4,0xb744b88a,0xb2ecb4c9,0xb408b599,0xab72b05d,0xac50b111,0x2e3724f5,0x2f3625bf,0x341e31a2,0x34ce328d,0x36e43577,0x3813366b,0x39093835,0x3a173906,
0xb8b9b99e,0xb9aabad7,0xb64db7d0,0xb768b8a2,0xb310b4e2,0xb41ab5b3,0xab98b074,0xac63b128,0x2e57250f,0x2f5525d8,0x343331c0,0x34e432aa,0x370b3595,0x3828368a,0x3929384e,0x3a3b3922,
0xb8d6b9c3,0xb9cabb02,0xb670b7fd,0xb78cb8ba,0xb335b4fc,0xb42db5ce,0xabbeb08a,0xac76b13e,0x2e772528,0x2f7525f1,0x344931dd,0x34fa32c8,0x373335b3,0x383d36a9,0x39493868,0x3a60393e,
0xb8f3b9e8,0xb9ebbb2d,0xb693b815,0xb7b1b8d2,0xb359b516,0xb43fb5e9,0xabe3b0a1,0xac89b155,0x2e972541,0x2f95260a,0x345f31fa,0x351132e5,0x375b35d2,0x385236c8,0x396a3881,0x3a86395a,
0xb910ba0e,0xba0cbb59,0xb6b6b82c,0xb7d6b8eb,0xb37db530,0xb452b604,0xac05b0b7,0xac9cb16b,0x2eb6255a,0x2fb52623,0x34753217,0x35273303,0x378335f0,0x386836e8,0x398c389b,0x3aac3977,
0xb92eba35,0xba2dbb87,0xb6d9b843,0xb7fbb904,0xb3a2b54a,0xb464b61e,0xac18b0ce,0xacafb182,0x2ed62573,0x2fd5263c,0x348b3235,0x353e3321,0x37ab360e,0x387d3708,0x39ae38b6,0x3ad33994,
0x9ce99db2,0xad3aae11,0x9aad9c20,0xab1aac63,0x9712991b,0xa783a96d,0x8a4893db,0x9aada42c,0x157f10b6,0x25d82102,0x19e41852,0x2a432897,0x1c841b76,0x2ccf2bf0,0x1e161d4d,0x2e7d2da6,
0xa35da445,0xadd8aec9,0xa102a22f,0xabf0ace8,0x9d4d9fa8,0xa833aa11,0x90b699e4,0x9b76a4aa,0x1c201712,0x26882199,0x206b1e7b,0x2b002922,0x22c62199,0x2d602c70,0x249123f4,0x2f422e51,
0xa623a71f,0xae77af82,0xa42ca528,0xac63ad6d,0xa06ba262,0xa8a4aab5,0x93db9ce9,0x9c20a528,0x1edf19e4,0x2738222f,0x235d2166,0x2bbe29ac,0x25a524aa,0x2df22ce8,0x279c26a1,0x30042efc,
0xa84ca8fc,0xaf16b01d,0xa5d8a738,0xaccfadf2,0xa22fa478,0xa915ab59,0x957f9edf,0x9c84a5a5,0x20d01c20,0x27e822c6,0x2528238f,0x2c3d2a37,0x27e82688,0x2e842d60,0x295428a4,0x30672fa8,
0xa987aa69,0xafb5b07a,0xa783a8a4,0xad3aae77,0xa3f4a5bf,0xa987abfd,0x9712a06b,0x9ce9a623,0x222f1d4d,0x284c235d,0x26a124dc,0x2c9c2ac1,0x29152833,0x2f162dd8,0x2adb29f8,0x30ca302a,
0xaac1abd7,0xb02ab0d7,0xa897a9ac,0xada6aefc,0xa4dca705,0xa9f8ac50,0x9852a166,0x9d4da6a1,0x238f1e7b,0x28a423f4,0x280d25f1,0x2cfb2b4c,0x2a372922,0x2fa82e51,0x2c312b4c,0x312e3081,
0xabfdaca2,0xb07ab135,0xa96daab5,0xae11af82,0xa5bfa826,0xaa69aca2,0x991ba262,0x9db2a71f,0x24781fa8,0x28fc2445,0x28ca2705,0x2d5a2bd7,0x2b592a11,0x301d2ec9,0x2cf52c50,0x319230d7,
0xac9cad5a,0xb0cab192,0xaa43abbe,0xae7db004,0xa6a1a8ca,0xaadbacf5,0x99e4a35d,0x9e16a79c,0x2528206b,0x29542491,0x2987280d,0x2db92c31,0x2c3d2b00,0x30672f42,0x2db92cfb,0x31f7312e,
0xb11bb1f0,0xb3a8b479,0xaee9b047,0xb128b266,0xab4cad47,0xad6dafdb,0x9e7ba80d,0xa0d0aa05,0x29ac24dc,0x2c372738,0x2e182c76,0x308a2ea3,0x30b12fbb,0x330631c6,0x325c3185,0x34cc3426,
0xb16bb24f,0xb3fcb4aa,0xaf55b08a,0xb15fb2aa,0xabbead99,0xada6b017,0x9edfa84c,0xa102aa43,0x2a052528,0x2c632783,0x2e772cbc,0x30ba2ee9,0x30fb301a,0x33523204,0x32c131dd,0x35013453,
0xb1bcb2ae,0xb428b4db,0xafc2b0ce,0xb196b2ef,0xac18adeb,0xaddfb041,0x9f44a88b,0xa134aa82,0x2a5d2573,0x2c9027cf,0x2ed62d01,0x30eb2f2f,0x31453057,0x339e3242,0x33273235,0x35373481,
0xb20eb30d,0xb452b50d,0xb017b111,0xb1cdb335,0xac50ae3e,0xae18b06a,0x9fa8a8ca,0xa166aac1,0x2ab525bf,0x2cbc280d,0x2f362d47,0x311b2f75,0x318f3094,0x33eb3280,0x338e328d,0x356d34af,
0xb25fb36d,0xb47cb540,0xb04db155,0xb204b37a,0xac89ae90,0xae51b094,0xa006a909,0xa199ab00,0x2b0d260a,0x2ce82833,0x2f952d8c,0x314b2fbb,0x31da30d1,0x341c32be,0x33f532e5,0x35a334dd,
0xb2b1b3cd,0xb4a6b572,0xb084b199,0xb23bb3c0,0xacc2aee3,0xae8ab0be,0xa039a948,0xa1cbab40,0x2b652655,0x2d142859,0x2ff52dd2,0x317c3001,0x3224310e,0x344332fc,0x342e333e,0x35da350c,
0xb303b417,0xb4d1b5a5,0xb0bab1dd,0xb273b403,0xacfbaf36,0xaec3b0e7,0xa06ba987,0xa1fdab7f,0x2bbe26a1,0x2d40287e,0x302a2e18,0x31ac3024,0x326f314b,0x3469333b,0x34633398,0x3612353a,
0xb356b448,0xb4fcb5d9,0xb0f1b221,0xb2aab426,0xad34af88,0xaefcb111,0xa09da9c6,0xa22fabbe,0x2c0b26ec,0x2d6d28a4,0x305a2e5e,0x31dd3047,0x32bb3189,0x3490337a,0x349733f2,0x364a3569,
0xb527b60d,0xb68bb7bd,0xb2e2b449,0xb453b569,0xaf36b13b,0xb081b28d,0xa262abfd,0xa3f4acfb,0x2d9928ca,0x2efc29f8,0x320e306a,0x33983185,0x34b733b9,0x35f934dd,0x36823599,0x382e3722,
0xb553b641,0xb6bab7f5,0xb31ab46d,0xb470b58e,0xaf6fb165,0xb09db2b7,0xa294ac1e,0xa413ad1b,0x2dc528f0,0x2f292a1e,0x323e308d,0x33ca31a9,0x34df33f8,0x362234fe,0x36bb35c9,0x384d3755,
0xb57eb676,0xb6e8b817,0xb352b490,0xb48db5b3,0xafa8b18f,0xb0bab2e2,0xa2c6ac3d,0xa42cad3a,0x2df22915,0x2f552a43,0x326f30b1,0x33fc31cd,0x3506341c,0x364c351f,0x36f535f9,0x386d3789,
0xb5abb6ab,0xb717b834,0xb38bb4b4,0xb4aab5d9,0xafe2b1b9,0xb0d7b30d,0xa2f9ac5d,0xa445ad5a,0x2e1e293b,0x2f822a69,0x32a130d4,0x341731f0,0x352e343c,0x36763540,0x372f3629,0x388d37bd,
0xb5d7b6e0,0xb746b851,0xb3c3b4d8,0xb4c7b5fe,0xb00eb1e3,0xb0f4b338,0xa32bac7d,0xa45fad79,0x2e4b2961,0x2faf2a8f,0x32d230f7,0x34303214,0x3556345c,0x36a03561,0x376a365a,0x38ad37f1,
0xb604b717,0xb775b86f,0xb3fcb4fc,0xb4e4b624,0xb02ab20e,0xb111b363,0xa35dac9c,0xa478ad99,0x2e772987,0x2fdb2ab5,0x3303311b,0x34493238,0x357e347c,0x36ca3582,0x37a5368b,0x38ce3813,
0xb631b74d,0xb7a5b88d,0xb41ab520,0xb501b64a,0xb047b238,0xb12eb38e,0xa38facbc,0xa491adb9,0x2ea329ac,0x30042adb,0x3335313e,0x3463325c,0x35a7349c,0x36f535a3,0x37e236bd,0x38f0382e,
0xb65eb785,0xb7d6b8ab,0xb437b545,0xb51fb670,0xb064b262,0xb14bb3b9,0xa3c2acdb,0xa4aaadd8,0x2ed029d2,0x301a2b00,0x33663162,0x347c3280,0x35d034bd,0x372035c5,0x380f36ef,0x39113849,
0xb803b8ca,0xb8d0b9d0,0xb53cb697,0xb62db7d4,0xb168b3e4,0xb252b4a1,0xa4c3adf8,0xa58caef6,0x30312b26,0x30e42c2b,0x349532a4,0x356433c6,0x374c35e7,0x385a36fc,0x39343865,0x3a5c394d,
0xb81cb8e9,0xb8ebb9f3,0xb55ab6bd,0xb64cb7fd,0xb185b408,0xb26fb4b7,0xa4dcae18,0xa5a5af16,0x30472b4c,0x30fb2c3d,0x34af32c8,0x357e33eb,0x37773609,0x38723720,0x39573880,0x3a84396b,
0xb835b909,0xb906ba17,0xb577b6e4,0xb66bb813,0xb1a2b41e,0xb28db4ce,0xa4f5ae37,0xa5bfaf36,0x305d2b72,0x31112c50,0x34c932ec,0x35993408,0x37a4362b,0x388a3744,0x397a389c,0x3aad398a,
0xb84eb929,0xb922ba3b,0xb595b70b,0xb68ab828,0xb1c0b433,0xb2aab4e4,0xa50fae57,0xa5d8af55,0x30742b98,0x31282c63,0x34e23310,0x35b3341a,0x37d0364d,0x38a23768,0x399e38b9,0x3ad739aa,
0xb868b949,0xb93eba60,0xb5b3b733,0xb6a9b83d,0xb1ddb449,0xb2c8b4fa,0xa528ae77,0xa5f1af75,0x308a2bbe,0x313e2c76,0x34fc3335,0x35ce342d,0x37fd3670,0x38ba378c,0x39c338d6,0x3b0239ca,
0xb881b96a,0xb95aba86,0xb5d2b75b,0xb6c8b852,0xb1fab45f,0xb2e5b511,0xa541ae97,0xa60aaf95,0x30a12be3,0x31552c89,0x35163359,0x35e9343f,0x38153693,0x38d237b1,0x39e838f3,0x3b2d39eb,
0xb89bb98c,0xb977baac,0xb5f0b783,0xb6e8b868,0xb217b475,0xb303b527,0xa55aaeb6,0xa623afb5,0x30b72c05,0x316b2c9c,0x3530337d,0x36043452,0x382c36b6,0x38eb37d6,0x3a0e3910,0x3b593a0c,
0xb8b6b9ae,0xb994bad3,0xb60eb7ab,0xb708b87d,0xb235b48b,0xb321b53e,0xa573aed6,0xa63cafd5,0x30ce2c18,0x31822caf,0x354a33a2,0x361e3464,0x384336d9,0x390437fb,0x3a35392e,0x3b873a2d,
0x214d2216,0x319b326c,0x1f762084,0x2fe830c8,0x1c521de4,0x2c962e40,0x14b6197f,0x250229d7,0x97db8e48,0xa82c9ead,0x9d1b9b12,0xad6bab82,0xa0209ead,0xb05eaf14,0xa1b2a0e9,0xb204b131,
0x27f32890,0x3241332b,0x259826c6,0x306a3156,0x227b246b,0x2d202efb,0x1b122020,0x25982a87,0x9de494b6,0xa8aa9f76,0xa3a8a14d,0xae0eac32,0xa62fa502,0xb0e1afe8,0xa845a75d,0xb2b6b1cc,
0x2aa02b9b,0x32e733e8,0x28aa29a5,0x30e131e5,0x2566275d,0x2daa2fb6,0x1de422df,0x262f2b36,0xa0e997db,0xa927a020,0xa661a46b,0xaeb0aca2,0xa927a82c,0xb163b05e,0xab1daa22,0xb368b266,
0x2ca22d52,0x338d3452,0x2a872be6,0x31563273,0x278f2927,0x2e333039,0x202024cf,0x26c62be6,0xa2df997f,0xa9a5a084,0xa877a62f,0xaf53ad13,0xab36a9d7,0xb1e5b0c8,0xacfaac4b,0xb40cb300,
0x2df52ed6,0x341834b0,0x2c322d13,0x31cc3300,0x28dc2aa0,0x2ebd3096,0x214d262f,0x275d2c4b,0xa46b9b12,0xaa22a0e9,0xa9bea7f3,0xaff5ad84,0xaca2ab82,0xb266b131,0xae65ad84,0xb464b399,
0x2f46302c,0x346a350c,0x2d202e33,0x3241338d,0x29f02c0c,0x2f4630f3,0x227b278f,0x27f32ca2,0xa5669c52,0xaaa0a14d,0xab04a8dc,0xb04badf5,0xadaaac96,0xb2e7b19b,0xafcfaebd,0xb4bcb418,
0x304b30ed,0x34bc3568,0x2e0e2f53,0x32b6340c,0x2b042cc8,0x2fcf3150,0x23a82877,0x28452cfa,0xa6619d1b,0xab1da1b2,0xac25a9be,0xb09cae65,0xaeb0ad6b,0xb368b204,0xb09caff5,0xb512b464,
0x30f331ad,0x350c35c4,0x2efb3039,0x332b3452,0x2c0c2d84,0x302c31ad,0x246b2927,0x28902d52,0xa75d9de4,0xab9ba216,0xacc8aaa0,0xb0edaed6,0xafb6ae40,0xb3e8b26c,0xb150b096,0xb568b4b0,
0x355d361e,0x37c63867,0x339f3497,0x359836b4,0x3071320a,0x32913473,0x28dc2daa,0x2b363032,0xac0ca27b,0xae01a4cf,0xb13eaf46,0xb3bdb163,0xb434b2d5,0xb627b506,0xb5beb4fa,0xb826b73e,
0x35ac3678,0x3808388f,0x340934dd,0x35cf36f5,0x30b53266,0x32d534a0,0x29272e01,0x2b82305e,0xac4ba2df,0xae40a502,0xb18eafb6,0xb406b19b,0xb473b33d,0xb663b539,0xb612b545,0xb84cb784,
0x35fb36d0,0x382c38b7,0x34433521,0x36073736,0x30f932c2,0x331834ce,0x29722e59,0x2bcd308a,0xac89a344,0xae7ea534,0xb1dfb013,0xb42eb1d2,0xb4b3b3a5,0xb6a0b56b,0xb666b58f,0xb872b7c9,
0x36493728,0x385038de,0x347c3565,0x363e3776,0x313e331e,0x335c34fa,0x29be2eb0,0x2c0c30b5,0xacc8a3a8,0xaebda566,0xb22fb04b,0xb455b20a,0xb4f1b406,0xb6dcb59d,0xb6b9b5d8,0xb898b807,
0x3697377e,0x38743904,0x34b635a9,0x367537b6,0x3182337a,0x339f3527,0x2a092f08,0x2c3230e1,0xad07a406,0xaefba598,0xb27fb083,0xb47cb241,0xb530b43a,0xb717b5cf,0xb70cb621,0xb8bdb828,
0x36e437d4,0x3897392a,0x34ee35ed,0x36ab37f5,0x31c633d6,0x33e23554,0x2a542f5f,0x2c57310c,0xad45a439,0xaf3aa5cb,0xb2cfb0bb,0xb4a4b279,0xb56eb46d,0xb752b601,0xb75db669,0xb8e1b84a,
0x37303814,0x38b9394e,0x3527362f,0x36e1381a,0x320a3418,0x34123580,0x2aa02fb6,0x2c7d3137,0xad84a46b,0xaf78a5fd,0xb31eb0f3,0xb4cbb2b0,0xb5acb4a0,0xb78cb632,0xb7adb6b1,0xb905b86b,
0x377c383e,0x38db3972,0x355f3672,0x37173838,0x324e3446,0x343435ac,0x2aeb3007,0x2ca23163,0xadc3a49d,0xafb6a62f,0xb36eb12b,0xb4f1b2e7,0xb5eab4d4,0xb7c6b663,0xb7fdb6f8,0xb928b88b,
0x38fd3996,0x39f33a91,0x374c3857,0x3874393e,0x345535d8,0x355d3730,0x2cc8318e,0x2df532e7,0xaff5a661,0xb0f3a7f3,0xb518b31e,0xb649b46a,0xb800b694,0xb8dbb808,0xb94bb8ab,0xba45b99b,
0x391e39b8,0x3a0f3aad,0x37813875,0x388c3959,0x34763604,0x357d375a,0x2cee31b9,0x2e1a3312,0xb01aa694,0xb112a813,0xb53fb356,0xb66fb485,0xb81cb6c5,0xb8f5b81f,0xb96db8cb,0xba61b9b7,
0x393e39da,0x3a2b3ac7,0x37b63893,0x38a53974,0x3497362f,0x359d3784,0x2d1331e5,0x2e40333d,0xb039a6c6,0xb131a82c,0xb565b38d,0xb694b4a0,0xb838b6f5,0xb90fb836,0xb98eb8ea,0xba7cb9d2,
0x395e39fb,0x3a453ae0,0x37ea38b0,0x38bd398e,0x34b9365b,0x35be37ad,0x2d393210,0x2e653368,0xb058a6f8,0xb150a845,0xb58cb3c3,0xb6b9b4bc,0xb854b725,0xb928b84c,0xb9aeb909,0xba97b9ed,
0x397d3a1b,0x3a5f3af9,0x380f38cd,0x38d539a8,0x34da3686,0x35de37d7,0x2d5e323b,0x2e8b3393,0xb077a72a,0xb16fa85e,0xb5b2b3fa,0xb6deb4d7,0xb870b755,0xb941b863,0xb9ceb927,0xbab0ba07,
0x399b3a3a,0x3a793b10,0x382838ea,0x38ed39c1,0x34fa36b1,0x35fe3800,0x2d843266,0x2eb033bd,0xb096a75d,0xb18ea877,0xb5d8b418,0xb703b4f1,0xb88bb784,0xb95ab879,0xb9edb945,0xbac9ba21,
0x39b93a58,0x3a913b26,0x38423906,0x390439da,0x351b36dc,0x361e3814,0x2daa3291,0x2ed633e8,0xb0b5a78f,0xb1ada890,0xb5feb434,0xb728b50c,0xb8a6b7b3,0xb972b88f,0xba0bb962,0xbae0ba3a,
0x39d73a75,0x3aa93b3c,0x385b3922,0x391b39f2,0x353c3706,0x363e3828,0x2dcf32bc,0x2efb3409,0xb0d4a7c1,0xb1cca8aa,0xb624b44f,0xb74cb527,0xb8c1b7e2,0xb98ab8a5,0xba29b97f,0xbaf7ba52,
0x3ac03b50,0x3b5e3bcb,0x39323a0a,0x39de3ab8,0x365e383c,0x375738d7,0x2f21341f,0x302634c8,0xb1eba8c3,0xb2e1a98c,0xb770b542,0xb846b615,0xb9a2b8bb,0xba51b960,0xbb0dba6a,0xbb9cbb11,
0x3ad73b63,0x3b6e3bd6,0x39493a22,0x39f23acb,0x367d3850,0x377638ea,0x2f463434,0x303934dd,0xb20aa8dc,0xb300a9a5,0xb795b55d,0xb857b62f,0xb9b9b8d0,0xba65b974,0xbb22ba81,0xbba9bb24,
0x3aec3b75,0x3b7d3bdf,0x395f3a39,0x3a063ade,0x369d3864,0x379538fd,0x2f6c3449,0x304b34f1,0xb229a8f5,0xb31ea9be,0xb7b8b577,0xb868b649,0xb9d0b8e5,0xba79b987,0xbb36ba97,0xbbb6bb35,
0x3b013b86,0x3b8c3be7,0x39753a4f,0x3a193af0,0x36bc3878,0x37b3390f,0x2f91345e,0x305e3506,0xb247a90e,0xb33da9d7,0xb7dcb592,0xb879b663,0xb9e7b8fa,0xba8cb99a,0xbb4abaad,0xbbc2bb46,
0x3b153b96,0x3b993bee,0x398a3a65,0x3a2d3b02,0x36dc388b,0x37d13921,0x2fb63473,0x3071351b,0xb266a927,0xb35ca9f0,0xb800b5ac,0xb88ab67d,0xb9fdb90f,0xba9fb9ad,0xbb5cbac3,0xbbccbb56,
0x3b283ba5,0x3ba63bf4,0x39a03a7a,0x3a3f3b13,0x36fb389e,0x37ef3933,0x2fdc3488,0x30833530,0xb285a940,0xb37aaa09,0xb811b5c7,0xb89bb697,0xba12b924,0xbab1b9c0,0xbb6dbad7,0xbbd6bb65,
0x3b3b3bb3,0x3bb23bf9,0x39b53a8f,0x3a523b24,0x371a38b2,0x38073945,0x3001349d,0x30963545,0xb2a4a959,0xb399aa22,0xb823b5e1,0xb8abb6b1,0xba28b938,0xbac3b9d2,0xbb7ebaeb,0xbbdfbb74,
0x3b4d3bc0,0x3bbd3bfc,0x39ca3aa4,0x3a643b34,0x373938c5,0x38153957,0x301334b3,0x30a9355a,0xb2c2a972,0xb3b7aa3b,0xb834b5fb,0xb8bcb6ca,0xba3cb94c,0xbad4b9e4,0xbb8dbaff,0xbbe6bb82,
0x20e921b2,0x31313204,0x1ead2020,0x2f14305e,0x1b121d1b,0x2b822d6b,0xe4817db,0x1ead282c,0x997f94b6,0xa9d7a502,0x9de49c52,0xae40ac96,0xa0849f76,0xb0c8afe8,0xa216a14d,0xb26cb19b,
0x275d2845,0x31cc32b6,0x2502262f,0x2fe830e1,0x214d23a8,0x2c322e0e,0x14b61de4,0x1f7628aa,0xa0209b12,0xaa87a598,0xa46ba27b,0xaefbad20,0xa6c6a598,0xb156b06a,0xa890a7f3,0xb32bb241,
0x2a222b1d,0x32663368,0x282c2927,0x305e3163,0x246b2661,0x2ca22eb0,0x17db20e9,0x20202927,0xa2df9de4,0xab36a62f,0xa75da566,0xafb6adaa,0xa9a5a8aa,0xb1e5b0e1,0xab9baaa0,0xb3e8b2e7,
0x2c4b2cfa,0x3300340c,0x29d72b36,0x30c831e5,0x262f2877,0x2d132f53,0x197f22df,0x208429a5,0xa4cfa020,0xabe6a6c6,0xa927a78f,0xb039ae33,0xabe6aa87,0xb273b156,0xad52aca2,0xb452b38d,
0x2d842e65,0x33993464,0x2b822ca2,0x31313266,0x27f329be,0x2d842ff5,0x1b12246b,0x20e92a22,0xa62fa14d,0xac4ba75d,0xaaa0a8dc,0xb096aebd,0xad13ac32,0xb300b1cc,0xaed6adf5,0xb4b0b418,
0x2ebd2fcf,0x341834bc,0x2c962daa,0x319b32e7,0x28dc2b04,0x2df5304b,0x1c522566,0x214d2aa0,0xa78fa27b,0xaca2a7f3,0xac0ca9f0,0xb0f3af46,0xae33ad20,0xb38db241,0xb02caf46,0xb50cb46a,
0x2ff5309c,0x34643512,0x2d6b2eb0,0x32043368,0x29be2c25,0x2e65309c,0x1d1b2661,0x21b22b1d,0xa877a3a8,0xacfaa845,0xacc8ab04,0xb150afcf,0xaf53ae0e,0xb40cb2b6,0xb0edb04b,0xb568b4bc,
0x30963150,0x34b03568,0x2e402fb6,0x326c33e8,0x2aa02cc8,0x2ed630ed,0x1de4275d,0x22162b9b,0xa927a46b,0xad52a890,0xad84ac0c,0xb1adb02c,0xb039aefb,0xb452b32b,0xb1adb0f3,0xb5c4b50c,
0x34fa35be,0x373e3826,0x32d53434,0x35063627,0x2f46313e,0x316333bd,0x227b2c0c,0x24cf2e01,0xadaaa8dc,0xb032ab36,0xb20ab071,0xb473b291,0xb497b39f,0xb6b4b598,0xb61eb55d,0xb867b7c6,
0x35453612,0x3784384c,0x333d3473,0x35393663,0x2fb6318e,0x319b3406,0x22df2c4b,0x25022e40,0xae01a927,0xb05eab82,0xb266b0b5,0xb4a0b2d5,0xb4ddb409,0xb6f5b5cf,0xb678b5ac,0xb88fb808,
0x358f3666,0x37c93872,0x33a534b3,0x356b36a0,0x301331df,0x31d2342e,0x23442c89,0x25342e7e,0xae59a972,0xb08aabcd,0xb2c2b0f9,0xb4ceb318,0xb521b443,0xb736b607,0xb6d0b5fb,0xb8b7b82c,
0x35d836b9,0x38073898,0x340634f1,0x359d36dc,0x304b322f,0x320a3455,0x23a82cc8,0x25662ebd,0xaeb0a9be,0xb0b5ac0c,0xb31eb13e,0xb4fab35c,0xb565b47c,0xb776b63e,0xb728b649,0xb8deb850,
0x3621370c,0x382838bd,0x343a3530,0x35cf3717,0x3083327f,0x3241347c,0x24062d07,0x25982efb,0xaf08aa09,0xb0e1ac32,0xb37ab182,0xb527b39f,0xb5a9b4b6,0xb7b6b675,0xb77eb697,0xb904b874,
0x3669375d,0x384a38e1,0x346d356e,0x36013752,0x30bb32cf,0x327934a4,0x24392d45,0x25cb2f3a,0xaf5faa54,0xb10cac57,0xb3d6b1c6,0xb554b3e2,0xb5edb4ee,0xb7f5b6ab,0xb7d4b6e4,0xb92ab897,
0x36b137ad,0x386b3905,0x34a035ac,0x3632378c,0x30f3331e,0x32b034cb,0x246b2d84,0x25fd2f78,0xafb6aaa0,0xb137ac7d,0xb418b20a,0xb580b412,0xb62fb527,0xb81ab6e1,0xb814b730,0xb94eb8b9,
0x36f837fd,0x388b3928,0x34d435ea,0x366337c6,0x312b336e,0x32e734f1,0x249d2dc3,0x262f2fb6,0xb007aaeb,0xb163aca2,0xb446b24e,0xb5acb434,0xb672b55f,0xb838b717,0xb83eb77c,0xb972b8db,
0x38ab394b,0x399b3a45,0x36943800,0x380838db,0x331e3518,0x346a3649,0x26612ff5,0x27f330f3,0xb18eacc8,0xb2e7adf5,0xb5d8b455,0xb730b55d,0xb857b74c,0xb93eb874,0xb996b8fd,0xba91b9f3,
0x38cb396d,0x39b73a61,0x36c5381c,0x381f38f5,0x3356353f,0x3485366f,0x2694301a,0x28133112,0xb1b9acee,0xb312ae1a,0xb604b476,0xb75ab57d,0xb875b781,0xb959b88c,0xb9b8b91e,0xbaadba0f,
0x38ea398e,0x39d23a7c,0x36f53838,0x3836390f,0x338d3565,0x34a03694,0x26c63039,0x282c3131,0xb1e5ad13,0xb33dae40,0xb62fb497,0xb784b59d,0xb893b7b6,0xb974b8a5,0xb9dab93e,0xbac7ba2b,
0x390939ae,0x39ed3a97,0x37253854,0x384c3928,0x33c3358c,0x34bc36b9,0x26f83058,0x28453150,0xb210ad39,0xb368ae65,0xb65bb4b9,0xb7adb5be,0xb8b0b7ea,0xb98eb8bd,0xb9fbb95e,0xbae0ba45,
0x392739ce,0x3a073ab0,0x37553870,0x38633941,0x33fa35b2,0x34d736de,0x272a3077,0x285e316f,0xb23bad5e,0xb393ae8b,0xb686b4da,0xb7d7b5de,0xb8cdb80f,0xb9a8b8d5,0xba1bb97d,0xbaf9ba5f,
0x394539ed,0x3a213ac9,0x3784388b,0x3879395a,0x341835d8,0x34f13703,0x275d3096,0x2877318e,0xb266ad84,0xb3bdaeb0,0xb6b1b4fa,0xb800b5fe,0xb8eab828,0xb9c1b8ed,0xba3ab99b,0xbb10ba79,
0x39623a0b,0x3a3a3ae0,0x37b338a6,0x388f3972,0x343435fe,0x350c3728,0x278f30b5,0x289031ad,0xb291adaa,0xb3e8aed6,0xb6dcb51b,0xb814b61e,0xb906b842,0xb9dab904,0xba58b9b9,0xbb26ba91,
0x397f3a29,0x3a523af7,0x37e238c1,0x38a5398a,0x344f3624,0x3527374c,0x27c130d4,0x28aa31cc,0xb2bcadcf,0xb409aefb,0xb706b53c,0xb828b63e,0xb922b85b,0xb9f2b91b,0xba75b9d7,0xbb3cbaa9,
0x3a6a3b0d,0x3b113b9c,0x38bb39a2,0x39603a51,0x35423770,0x36153846,0x28c331eb,0x298c32e1,0xb41faf21,0xb4c8b026,0xb83cb65e,0xb8d7b757,0xba0ab932,0xbab8b9de,0xbb50bac0,0xbbcbbb5e,
0x3a813b22,0x3b243ba9,0x38d039b9,0x39743a65,0x355d3795,0x362f3857,0x28dc320a,0x29a53300,0xb434af46,0xb4ddb039,0xb850b67d,0xb8eab776,0xba22b949,0xbacbb9f2,0xbb63bad7,0xbbd6bb6e,
0x3a973b36,0x3b353bb6,0x38e539d0,0x39873a79,0x357737b8,0x36493868,0x28f53229,0x29be331e,0xb449af6c,0xb4f1b04b,0xb864b69d,0xb8fdb795,0xba39b95f,0xbadeba06,0xbb75baec,0xbbdfbb7d,
0x3aad3b4a,0x3b463bc2,0x38fa39e7,0x399a3a8c,0x359237dc,0x36633879,0x290e3247,0x29d7333d,0xb45eaf91,0xb506b05e,0xb878b6bc,0xb90fb7b3,0xba4fb975,0xbaf0ba19,0xbb86bb01,0xbbe7bb8c,
0x3ac33b5c,0x3b563bcc,0x390f39fd,0x39ad3a9f,0x35ac3800,0x367d388a,0x29273266,0x29f0335c,0xb473afb6,0xb51bb071,0xb88bb6dc,0xb921b7d1,0xba65b98a,0xbb02ba2d,0xbb96bb15,0xbbeebb99,
0x3ad73b6d,0x3b653bd6,0x39243a12,0x39c03ab1,0x35c73811,0x3697389b,0x29403285,0x2a09337a,0xb488afdc,0xb530b083,0xb89eb6fb,0xb933b7ef,0xba7ab9a0,0xbb13ba3f,0xbba5bb28,0xbbf4bba6,
0x3aeb3b7e,0x3b743bdf,0x39383a28,0x39d23ac3,0x35e13823,0x36b138ab,0x295932a4,0x2a223399,0xb49db001,0xb545b096,0xb8b2b71a,0xb945b807,0xba8fb9b5,0xbb24ba52,0xbbb3bb3b,0xbbf9bbb2,
0x3aff3b8d,0x3b823be6,0x394c3a3c,0x39e43ad4,0x35fb3834,0x36ca38bc,0x297232c2,0x2a3b33b7,0xb4b3b013,0xb55ab0a9,0xb8c5b739,0xb957b815,0xbaa4b9ca,0xbb34ba64,0xbbc0bb4d,0xbbfcbbbd,
0x39b839ba,0x3a973ab5,0x39b339b5,0x3a583a78,0x39af39b1,0x3a153a37,0x39aa39ad,0x39cd39f2,0x39a639a8,0x398239a8,0x39a139a4,0x3933395b,0x399d399f,0x38e03909,0x3999399b,0x388938b5,
0xb979b972,0xb865b832,0xb986b980,0xb8c7b896,0xb994b98d,0xb924b8f6,0xb9a1b99b,0xb97db951,0xb9afb9a8,0xb9d2b9a8,0xb9bcb9b5,0xba21b9fa,0xb9c9b9c3,0xba6bba47,0xb9d6b9d0,0xbab0ba8e,
0xb9f4b9fe,0xbac7bae9,0xb9dfb9e9,0xba7ebaa3,0xb9c9b9d4,0xba2dba56,0xb9b3b9be,0xb9d6ba02,0xb99db9a8,0xb979b9a8,0xb986b992,0xb916b948,0xb970b97b,0xb8adb8e2,0xb958b964,0xb840b877,
0x39373927,0x381a37b7,0x39583948,0x38943858,0x39793969,0x390738ce,0x39993989,0x3974393e,0x39b839a8,0x39da39a8,0x39d639c7,0x3a393a0b,0x39f439e5,0x3a903a65,0x3a113a02,0x3ade3ab8,
0x3a2d3a3f,0x3af43b1a,0x3a093a1b,0x3aa23acc,0x39e339f6,0x3a453a74,0x39bc39d0,0x39df3a13,0x399439a8,0x397039a8,0x396b3980,0x38f83935,0x39413956,0x387a38ba,0x3916392b,0x37e83838,
0xb8f3b8d8,0xb79bb705,0xb929b90e,0xb85fb817,0xb95db943,0xb8eab8a6,0xb990b976,0xb96bb92b,0xb9c0b9a8,0xb9e3b9a8,0xb9f0b9d8,0xba50ba1b,0xba1dba07,0xbab3ba83,0xba49ba33,0xbb0abae0,
0xba64ba7c,0xbb1ebb46,0xba31ba4b,0xbac4baf3,0xb9fcba17,0xba5cba92,0xb9c5b9e1,0xb9e7ba23,0xb98bb9a8,0xb966b9a8,0xb94fb96d,0xb8dbb922,0xb911b930,0xb845b891,0xb8d1b8f1,0xb74eb7ee,
0x38ad3887,0x36ff364e,0x38f838d3,0x382a37ac,0x3941391d,0x38cc387c,0x39863964,0x39623918,0x39c939a8,0x39eb39a8,0x3a0939e9,0x3a673a2b,0x3a453a27,0x3ad53aa0,0x3a7e3a62,0x3b323b05,
0x3b453b6e,0x3bbc3bdd,0x3ae53b17,0x3b573b8f,0x3a733aae,0x3ac73b14,0x39f03a33,0x3a113a71,0x395d39a8,0x393739a8,0x38bc390e,0x384038bf,0x380f3867,0x365f3775,0x36af376a,0x341a3540,
0xb65fb593,0xb389b115,0xb7e8b726,0xb625b4f9,0xb8adb852,0xb830b748,0xb958b905,0xb933b8b5,0xb9f4b9a8,0xba15b9a8,0xba7eba3b,0xbad1ba78,0xbaf4babc,0xbb63bb20,0xbb57bb28,0xbbc6bb9b,
0xbb68bb91,0xbbd0bbed,0xbb04bb39,0xbb6fbba6,0xba89bac9,0xbadbbb2b,0xb9f8ba43,0xba19ba7f,0xb954b9a8,0xb92eb9a8,0xb89eb8fb,0xb820b8ab,0xb7b2b83d,0xb5ebb71b,0xb60eb6e3,0xb2deb4b1,
0x35bc34d5,0x32322f0e,0x377a369e,0x35b13469,0x388e3828,0x380f36ee,0x394f38f1,0x392938a0,0x39fc39a8,0x3a1d39a8,0x3a933a4b,0x3ae53a87,0x3b133ad6,0x3b7a3b36,0x3b783b49,0x3bd93bb1,
0x3b873baf,0x3be13bf8,0x3b213b58,0x3b853bbb,0x3a9e3ae3,0x3aee3b41,0x3a003a52,0x3a213a8e,0x394a39a8,0x392439a8,0x387f38e7,0x37fe3896,0x37423812,0x357636c1,0x356a3659,0x31853420,
0xb517b414,0xb0d7abd9,0xb70ab614,0xb53ab3ae,0xb86fb7f9,0xb7ddb693,0xb946b8dd,0xb91fb88c,0xba04b9a8,0xba25b9a8,0xbaa9ba5a,0xbaf7ba95,0xbb2fbaf0,0xbb90bb4b,0xbb96bb67,0xbbe8bbc4,
0xbba3bbc9,0xbbefbbff,0xbb3dbb74,0xbb9abbcd,0xbab3bafc,0xbb01bb55,0xba09ba62,0xba29ba9c,0xb941b9a8,0xb91bb9a8,0xb85fb8d3,0xb7bdb881,0xb6d2b7cd,0xb4ffb665,0xb4c3b5ce,0xb029b31b,
0x346f32a1,0x2ef52248,0x36993587,0x34c33288,0x385037a1,0x379b3637,0x393c38c9,0x39163877,0x3a0d39a8,0x3a2d39a8,0x3abd3a69,0x3b0a3aa3,0x3b4a3b08,0x3ba33b5f,0x3bb03b82,0x3bf43bd5,
0x3bf83c00,0x3bf93bd4,0x3bac3bdc,0x3be43bfe,0x3b133b69,0x3b543bab,0x3a313aaa,0x3a503ae0,0x391139a8,0x38ea39a8,0x377a386d,0x366b3817,0x34873608,0x313b348d,0x2d9731f4,0xad65291b,
0xac3828b6,0x2ec33365,0xb44bb160,0xb0bea57f,0xb759b5da,0xb648b45d,0xb90cb862,0xb8e5b80d,0xba35b9a8,0xba54b9a8,0xbb1bbab1,0xbb5cbae6,0xbbb5bb72,0xbbe9bbb2,0xbbfcbbe3,0xbbf5bc00,
0xbbfebbfc,0xbbefbbbc,0xbbbdbbe9,0xbbeebc00,0xbb24bb7b,0xbb63bbb9,0xba39bab8,0xba58baed,0xb907b9a8,0xb8e0b9a8,0xb737b858,0xb625b802,0xb40eb5ab,0xb042b42c,0xa9b1b0cb,0x30109a48,
0x25e4ad7e,0xb0beb475,0x33a23036,0x2f8ba3db,0x3715357c,0x360233f7,0x3902384d,0x38db37ee,0x3a3d39a8,0x3a5c39a8,0x3b2c3abf,0x3b6a3af3,0x3bc53b84,0x3bf23bc0,0x3bff3bee,0x3be93c00,
0x3c003bf4,0x3be23ba0,0x3bcc3bf3,0x3bf53bff,0x3b353b8c,0x3b713bc6,0x3a413ac6,0x3a603af9,0x38fd39a8,0x38d639a8,0x36f43842,0x35df37d8,0x3328354c,0x2e913396,0x16482f40,0xb16ca852,
0x251b304e,0x32193534,0xb2adae14,0xad972aac,0xb6d2b51d,0xb5bcb334,0xb8f8b838,0xb8d1b7c2,0xba45b9a8,0xba64b9a8,0xbb3dbacc,0xbb78baff,0xbbd3bb95,0xbbf8bbcb,0xbc00bbf7,0xbbdabbfd,
0xbbfebbe6,0xbbd2bb80,0xbbd9bbfa,0xbbfbbbfb,0xbb45bb9d,0xbb7fbbd1,0xba49bad3,0xba67bb05,0xb8f3b9a8,0xb8ccb9a8,0xb6afb82d,0xb599b7ac,0xb232b4ed,0xac9cb2d2,0x294dace7,0x32c62c83,
0xac06b1db,0xb371b5f1,0x31b62b75,0x2b43adb0,0x368d34bd,0x3576326f,0x38ee3822,0x38c73796,0x3a4d39a8,0x3a6b39a8,0x3b4c3ad9,0x3b853b0b,0x3bdf3ba4,0x3bfd3bd6,0x3bfc3bfd,0x3bc83bf8,
0x3bbd3b5a,0x3b473a99,0x3bfe3bf4,0x3bf93bbe,0x3b8b3bdb,0x3bb83bf7,0x3a6f3b11,0x3a8c3b3e,0x38c139a8,0x389939a8,0x35523780,0x343236cc,0x294d320d,0xad332de2,0xb40eaedc,0xb6a4b408,
0x346336aa,0x36f438b0,0xa6ad3004,0x2e2d3451,0xb52fb1aa,0xb40ead1a,0xb8bcb76a,0xb894b6b5,0xba73b9a8,0xba90b9a8,0xbb92bb17,0xbbbdbb43,0xbbffbbe0,0xbbf6bbf9,0xbbb2bbf0,0xbb35bbb4,
0xbba5bb30,0xbb21ba5e,0xbc00bbeb,0xbbf3bbaa,0xbb98bbe4,0xbbc2bbfb,0xba76bb1d,0xba93bb49,0xb8b7b9a8,0xb88eb9a8,0xb50bb753,0xb3d3b69e,0xa17fb147,0x2f27ac51,0x34b73099,0x37423499,
0xb50bb75e,0xb790b900,0x9cb6b12e,0xb010b4e1,0x34e730e4,0x33892b11,0x38b2373d,0x38893687,0x3a7a39a8,0x3a9739a8,0x3b9e3b22,0x3bc63b4e,0x3c003be8,0x3bef3bfd,0x3b983be5,0x3b0d3b9e,
0x3b893b02,0x3af73a1f,0x3c003bdf,0x3beb3b93,0x3ba33bec,0x3bcb3bfe,0x3a7e3b28,0x3a9b3b53,0x38ad39a8,0x388439a8,0x34c33726,0x33403670,0xa51b3080,0xb08d297f,0xb55eb1c3,0xb7ddb529,
0x35b13807,0x3815394d,0x28843257,0x31093570,0xb49fb01d,0xb2f7a7da,0xb8a8b710,0xb87fb659,0xba81b9a8,0xba9eb9a8,0xbba9bb2e,0xbbcfbb58,0xbbffbbef,0xbbe6bbff,0xbb7abbd7,0xbae1bb86,
0xbb6abad0,0xbacbb9dc,0xbbfdbbd0,0xbbe1bb79,0xbbaebbf2,0xbbd3bc00,0xba85bb33,0xbaa2bb5d,0xb8a3b9a8,0xb87ab9a8,0xb47bb6f9,0xb2adb642,0x2a7aaf72,0x3185a4b6,0x360232ea,0x383a35b6,
0xb654b85d,0xb85fb996,0xac38b37d,0xb201b5fd,0x34572eaa,0x32631e48,0x389e36e3,0x3874362b,0x3a8939a8,0x3aa539a8,0x3bb33b39,0x3bd73b62,0x3bfc3bf5,0x3bdc3c00,0x3b593bc7,0x3ab33b6b,
0x39b739b9,0x3a883aa6,0x39b239b4,0x3a483a68,0x39ae39b0,0x3a033a26,0x39a939ab,0x39bb39e0,0x39a539a7,0x396e3995,0x39a039a3,0x391e3947,0x399c399e,0x38ca38f5,0x3997399a,0x3873389f,
0xb97cb975,0xb87eb84c,0xb98ab983,0xb8deb8ae,0xb997b991,0xb93bb90d,0xb9a5b99e,0xb993b967,0xb9b2b9ab,0xb9e6b9bd,0xb9bfb9b9,0xba34ba0e,0xb9ccb9c6,0xba7dba59,0xb9d9b9d3,0xbac0ba9f,
0xb9efb9f9,0xbab6bad9,0xb9d9b9e4,0xba6aba91,0xb9c4b9cf,0xba18ba42,0xb9aeb9b9,0xb9bfb9ec,0xb997b9a3,0xb961b991,0xb981b98c,0xb8fcb92f,0xb96ab975,0xb892b8c8,0xb953b95e,0xb824b85c,
0x3940392f,0x383937f6,0x39613950,0x38b13876,0x39813971,0x392338eb,0x39a03991,0x398e395a,0x39bf39b0,0x39f339c1,0x39de39cf,0x3a4f3a22,0x39fb39ec,0x3aa43a7b,0x3a183a0a,0x3af03acb,
0x3a243a36,0x3ae13b07,0x39ff3a12,0x3a8b3ab7,0x39d939ec,0x3a2c3a5d,0x39b239c6,0x39c439f9,0x398a399e,0x3953398c,0x39613975,0x38d93917,0x3936394b,0x3859389a,0x390b3921,0x37a43816,
0xb901b8e6,0xb7e6b750,0xb936b91c,0xb883b83c,0xb96ab950,0xb90bb8c8,0xb99cb983,0xb98ab94b,0xb9ccb9b4,0xb9ffb9c6,0xb9fbb9e4,0xba6aba36,0xba28ba12,0xbacaba9b,0xba53ba3e,0xbb1dbaf5,
0xba57ba70,0xbb09bb33,0xba24ba3e,0xbaabbadc,0xb9efba0a,0xba40ba77,0xb9b7b9d3,0xb9c8ba05,0xb97cb99a,0xb944b988,0xb940b95e,0xb8b6b8fe,0xb901b921,0xb81eb86b,0xb8c0b8e1,0xb6fcb79e,
0x38c0389a,0x375636a7,0x390b38e6,0x38543800,0x3953392f,0x38f238a4,0x39973975,0x3985393d,0x39d939b9,0x3a0c39ca,0x3a1839f9,0x3a843a4a,0x3a533a36,0x3aed3abb,0x3a8b3a70,0x3b473b1c,
0x3b2e3b5a,0x3ba63bce,0x3aca3afe,0x3b373b74,0x3a533a91,0x3a9d3aef,0x39cc3a12,0x39de3a42,0x39363983,0x38fc3971,0x389238e6,0x37fb3880,0x37c5383c,0x35d136eb,0x3651370d,0x330934ae,
0xb6c3b5fa,0xb460b251,0xb824b788,0xb6b8b590,0xb8d9b880,0xb873b7d5,0xb981b92f,0xb96eb8f5,0xba18b9cf,0xba48b9e0,0xba9dba5d,0xbafabaa6,0xbb0fbad9,0xbb80bb43,0xbb6cbb40,0xbbd8bbb2,
0xbb51bb7d,0xbbbdbbe0,0xbae7bb1f,0xbb4ebb8c,0xba66baa9,0xbaafbb04,0xb9d1ba1e,0xb9e2ba4e,0xb928b97e,0xb8edb96c,0xb86eb8cd,0xb7afb866,0xb74bb80b,0xb54fb684,0xb5a2b679,0xb197b411,
0x362e3549,0x338330de,0x37e6370d,0x3651350e,0x38c0385c,0x38593788,0x397c3921,0x396a38e6,0x3a2439d3,0x3a5339e4,0x3ab63a70,0x3b0f3ab7,0x3b2e3af5,0x3b973b5a,0x3b8d3b61,0x3be83bc7,
0x3b703b9c,0x3bd03bef,0x3b033b3d,0x3b653ba2,0x3a793ac1,0x3ac03b19,0x39d53a2a,0x39e63a59,0x3919397a,0x38de3967,0x384938b4,0x3761384c,0x36cf37b4,0x34cc361d,0x34f035e2,0x302332e4,
0xb596b496,0xb244aecf,0xb783b690,0xb5e8b48a,0xb8a7b836,0xb83eb73a,0xb978b912,0xb965b8d7,0xba30b9d7,0xba5fb9e8,0xbacdba82,0xbb23bac8,0xbb4cbb10,0xbbacbb6f,0xbbaabb7f,0xbbf4bbd8,
0xbb8dbbb7,0xbbe0bbf9,0xbb1dbb5a,0xbb7abbb5,0xba8bbad9,0xbad0bb2d,0xb9d9ba36,0xb9eaba65,0xb90bb975,0xb8cfb963,0xb824b89a,0xb713b831,0xb651b750,0xb447b5b3,0xb43bb549,0xad58b1a4,
0x34fc33c0,0x31032bc0,0x371e3611,0x357e3405,0x388d3811,0x382436eb,0x39733903,0x396138c8,0x3a3c39db,0x3a6a39ec,0x3ae43a94,0x3b373ad9,0x3b673b2a,0x3bbe3b83,0x3bc33b9a,0x3bfc3be7,
0x3bed3bff,0x3bff3bea,0x3b8d3bc7,0x3bcc3bf5,0x3ae13b40,0x3b1d3b83,0x39ef3a70,0x39ff3a9b,0x38c0395e,0x3883394b,0x36c33816,0x357e3750,0x33833549,0x2e84332e,0x28cf3061,0xb0aca5b2,
0xaf7ea376,0x29663166,0xb514b2fd,0xb2bfad71,0xb809b69b,0xb734b555,0xb95cb8b9,0xb949b87b,0xba75b9f1,0xbaa1ba01,0xbb49bae9,0xbb8bbb25,0xbbcfbb96,0xbbf9bbd2,0xbc00bbf2,0xbbe3bbfe,
0xbbf6bc00,0xbbfcbbda,0xbb9fbbd6,0xbbd8bbfb,0xbaf0bb52,0xbb2cbb92,0xb9f3ba7b,0xba03baa6,0xb8b1b95a,0xb873b947,0xb673b7f6,0xb52cb718,0xb276b4de,0xac5eb251,0x2052ae39,0x321f2bf2,
0x2cf4a806,0xad3fb2d8,0x34a831ee,0x31e22a93,0x37db364b,0x36fc3502,0x395738a9,0x3944386b,0x3a8039f5,0x3aab3a05,0x3b5b3af8,0x3b993b33,0x3bdd3ba7,0x3bfd3bdd,0x3bff3bfa,0x3bd13bf9,
0x3bfd3bfd,0x3bf53bc6,0x3baf3be3,0x3be23bff,0x3b003b64,0x3b393ba0,0x39f73a86,0x3a083ab0,0x38a23955,0x38633942,0x362237bf,0x34d836e0,0x31663472,0x286b3172,0xaaf82b5c,0xb390ae84,
0xa8cf2cf4,0x2fc93423,0xb43bb0de,0xb103a484,0xb7a4b5fa,0xb6c3b4ae,0xb953b89a,0xb940b85c,0xba8bb9f9,0xbab6ba0a,0xbb6cbb07,0xbba6bb40,0xbbe8bbb7,0xbc00bbe7,0xbbfabbff,0xbbbabbf1,
0xbc00bbf6,0xbbebbbae,0xbbbebbed,0xbbebbc00,0xbb0fbb74,0xbb47bbad,0xb9fbba91,0xba0cbabb,0xb892b950,0xb854b93d,0xb5d1b788,0xb484b6a7,0xb055b405,0x9248b093,0x2e6ba484,0x347e3086,
0x98b6afe2,0xb128b4d8,0x339c2f97,0x3023a420,0x376c35a8,0x368a345a,0x394e388b,0x393b384c,0x3a9639fd,0x3ac03a0e,0x3b7c3b16,0x3bb33b4d,0x3bf23bc5,0x3c003bef,0x3bf03c00,0x3ba03be5,
0x3bde3b91,0x3b8a3af7,0x3bf23bff,0x3c003be3,0x3b533bb9,0x3b823bdf,0x3a103ac5,0x3a203aec,0x38443939,0x38033925,0x342f366d,0x31b03584,0xa8392f65,0xb15a1d7f,0xb531b1c9,0xb7e0b55b,
0x3269358a,0x35a83819,0xae842a61,0x205231e2,0xb651b405,0xb567b15a,0xb936b83c,0xb923b7f6,0xbacaba12,0xbaf0ba22,0xbbbebb5a,0xbbe3bb88,0xbbfdbbf5,0xbbddbc00,0xbb81bbd6,0xbadfbb7c,
0xbbcebb70,0xbb6dbac6,0xbbf8bbfb,0xbbffbbd6,0xbb60bbc4,0xbb8dbbe7,0xba14bacf,0xba24baf5,0xb834b934,0xb7e6b921,0xb3b4b634,0xb103b549,0x2c44ada3,0x326925b2,0x35e23309,0x384135f4,
0xb3a8b63a,0xb63fb869,0x2cc2ad58,0xa89db2f0,0x3617335f,0x352c30ac,0x3931382c,0x391e37d5,0x3ad43a16,0x3afa3a26,0x3bc93b66,0x3bea3b92,0x3bf93bfa,0x3bcf3bff,0x3b5f3bc5,0x3aad3b5d,
0x3bba3b4c,0x3b4d3a93,0x3bfc3bf6,0x3bfd3bc7,0x3b6c3bce,0x3b973bed,0x3a183ad9,0x3a283afe,0x3824392f,0x37c5391c,0x330935fa,0x3055350e,0xae6b2bc0,0xb377aa61,0xb690b423,0xb890b68a,
0x347236e5,0x36d438b6,0xa9fd2f7e,0x2c1233fd,0xb5dcb2b3,0xb4f0affb,0xb92db81c,0xb919b7b4,0xbaddba1a,0xbb03ba2a,0xbbd3bb72,0xbbf0bb9c,0xbbf2bbfe,0xbbbfbbfc,0xbb38bbaf,0xba77bb3c,
0xbba4bb23,0xbb2aba5b,0xbbffbbee,0xbbfabbb6,0xbb77bbd7,0xbba1bbf3,0xba1cbae2,0xba2cbb07,0xb813b92a,0xb7a4b917,0xb25db5bf,0xaf4cb4d2,0x3048a839,0x34412cf4,0x373a34c0,0x38dc371e,
0xb50eb78e,0xb767b901,0x24e9b0d1,0xadd5b484,0x35a23207,0x34b42e9d,0x3928380b,0x39143793,0x3ae73a1e,0x3b0c3a2e,0x3bdb3b7d,0x3bf53ba6,0x3be93c00,0x3bad3bf7,0x3b0d3b97,0x3a3e3b18,
0xb999b996,0xb889b85d,0xb99db99b,0xb8e0b8b5,0xb9a1b99f,0xb933b909,0xb9a6b9a4,0xb982b95b,0xb9aab9a8,0xb9cdb9a8,0xb9afb9ad,0xba15b9f2,0xb9b3b9b1,0xba58ba37,0xb9b8b9b5,0xba97ba78,
0xb9d6b9dc,0xbab0bad0,0xb9c9b9d0,0xba6bba8e,0xb9bcb9c3,0xba21ba47,0xb9afb9b5,0xb9d2b9fa,0xb9a1b9a8,0xb97db9a8,0xb994b99b,0xb924b951,0xb986b98d,0xb8c7b8f6,0xb979b980,0xb865b896,
0x3958394d,0x38403807,0x39703964,0x38ad3877,0x3986397b,0x391638e2,0x399d3992,0x39793948,0x39b339a8,0x39d639a8,0x39c939be,0x3a2d3a02,0x39df39d4,0x3a7e3a56,0x39f439e9,0x3ac73aa3,
0x3a113a1f,0x3ade3b02,0x39f43a02,0x3a903ab8,0x39d639e5,0x3a393a65,0x39b839c7,0x39da3a0b,0x399939a8,0x397439a8,0x39793989,0x3907393e,0x39583969,0x389438ce,0x39373948,0x381a3858,
0xb916b900,0xb7e8b75e,0xb941b92b,0xb87ab838,0xb96bb956,0xb8f8b8ba,0xb994b980,0xb970b935,0xb9bcb9a8,0xb9dfb9a8,0xb9e3b9d0,0xba45ba13,0xba09b9f6,0xbaa2ba74,0xba2dba1b,0xbaf4bacc,
0xba49ba5e,0xbb0abb30,0xba1dba33,0xbab3bae0,0xb9f0ba07,0xba50ba83,0xb9c0b9d8,0xb9e3ba1b,0xb990b9a8,0xb96bb9a8,0xb95db976,0xb8eab92b,0xb929b943,0xb85fb8a6,0xb8f3b90e,0xb79bb817,
0x38d138b0,0x374e36aa,0x391138f1,0x384537ee,0x394f3930,0x38db3891,0x398b396d,0x39663922,0x39c539a8,0x39e739a8,0x39fc39e1,0x3a5c3a23,0x3a313a17,0x3ac43a92,0x3a643a4b,0x3b1e3af3,
0x3a7e3a99,0x3b323b5a,0x3a453a62,0x3ad53b05,0x3a093a27,0x3a673aa0,0x39c939e9,0x39eb3a2b,0x398639a8,0x396239a8,0x39413964,0x38cc3918,0x38f8391d,0x382a387c,0x38ad38d3,0x36ff37ac,
0xb6afb5f1,0xb41ab1db,0xb80fb76a,0xb65fb540,0xb8bcb867,0xb840b775,0xb95db90e,0xb937b8bf,0xb9f0b9a8,0xba11b9a8,0xba73ba33,0xbac7ba71,0xbae5baae,0xbb57bb14,0xbb45bb17,0xbbbcbb8f,
0xbb57bb80,0xbbc6bbe6,0xbaf4bb28,0xbb63bb9b,0xba7ebabc,0xbad1bb20,0xb9f4ba3b,0xba15ba78,0xb958b9a8,0xb933b9a8,0xb8adb905,0xb830b8b5,0xb7e8b852,0xb625b748,0xb65fb726,0xb389b4f9,
0x360e3534,0x32de304e,0x37b236e3,0x35eb34b1,0x389e383d,0x3820371b,0x395438fb,0x392e38ab,0x39f839a8,0x3a1939a8,0x3a893a43,0x3adb3a7f,0x3b043ac9,0x3b6f3b2b,0x3b683b39,0x3bd03ba6,
0x3b783ba0,0x3bd93bf4,0x3b133b49,0x3b7a3bb1,0x3a933ad6,0x3ae53b36,0x39fc3a4b,0x3a1d3a87,0x394f39a8,0x392939a8,0x388e38f1,0x380f38a0,0x377a3828,0x35b136ee,0x35bc369e,0x32323469,
0xb56ab475,0xb185ad7e,0xb742b659,0xb576b420,0xb87fb812,0xb7feb6c1,0xb94ab8e7,0xb924b896,0xba00b9a8,0xba21b9a8,0xba9eba52,0xbaeeba8e,0xbb21bae3,0xbb85bb41,0xbb87bb58,0xbbe1bbbb,
0xbb96bbbc,0xbbe8bbfc,0xbb2fbb67,0xbb90bbc4,0xbaa9baf0,0xbaf7bb4b,0xba04ba5a,0xba25ba95,0xb946b9a8,0xb91fb9a8,0xb86fb8dd,0xb7ddb88c,0xb70ab7f9,0xb53ab693,0xb517b614,0xb0d7b3ae,
0x34c33365,0x302928b6,0x36d235ce,0x34ff331b,0x385f37cd,0x37bd3665,0x394138d3,0x391b3881,0x3a0939a8,0x3a2939a8,0x3ab33a62,0x3b013a9c,0x3b3d3afc,0x3b9a3b55,0x3ba33b74,0x3bef3bcd,
0x3bb03bd4,0x3bf43c00,0x3b4a3b82,0x3ba33bd5,0x3abd3b08,0x3b0a3b5f,0x3a0d3a69,0x3a2d3aa3,0x393c39a8,0x391639a8,0x385038c9,0x379b3877,0x369937a1,0x34c33637,0x346f3587,0x2ef53288,
0xad972248,0x2d6532a1,0xb487b1f4,0xb13ba91b,0xb77ab608,0xb66bb48d,0xb911b86d,0xb8eab817,0xba31b9a8,0xba50b9a8,0xbb13baaa,0xbb54bae0,0xbbacbb69,0xbbe4bbab,0xbbf8bbdc,0xbbf9bbfe,
0xbbfcbbff,0xbbf5bbc9,0xbbb5bbe3,0xbbe9bc00,0xbb1bbb72,0xbb5cbbb2,0xba35bab1,0xba54bae6,0xb90cb9a8,0xb8e5b9a8,0xb759b862,0xb648b80d,0xb44bb5da,0xb0beb45d,0xac38b160,0x2ec3a57f,
0x29b1abd9,0xb010b414,0x340e30cb,0x30421a48,0x373735ab,0x3625342c,0x39073858,0x38e03802,0x3a3939a8,0x3a5839a8,0x3b243ab8,0x3b633aed,0x3bbd3b7b,0x3bee3bb9,0x3bfe3be9,0x3bef3c00,
0x3bff3bf8,0x3be93baf,0x3bc53bee,0x3bf23c00,0x3b2c3b84,0x3b6a3bc0,0x3a3d3abf,0x3a5c3af3,0x390239a8,0x38db39a8,0x3715384d,0x360237ee,0x33a2357c,0x2f8b33f7,0x25e43036,0xb0bea3db,
0x96482f0e,0x316c34d5,0xb328af40,0xae912852,0xb6f4b54c,0xb5dfb396,0xb8fdb842,0xb8d6b7d8,0xba41b9a8,0xba60b9a8,0xbb35bac6,0xbb71baf9,0xbbccbb8c,0xbbf5bbc6,0xbc00bbf3,0xbbe2bbff,
0xbc00bbed,0xbbdabb91,0xbbd3bbf7,0xbbf8bbfd,0xbb3dbb95,0xbb78bbcb,0xba45bacc,0xba64baff,0xb8f8b9a8,0xb8d1b9a8,0xb6d2b838,0xb5bcb7c2,0xb2adb51d,0xad97b334,0x251bae14,0x32192aac,
0xa94db115,0xb2c6b593,0x32322ce7,0x2c9cac83,0x36af34ed,0x359932d2,0x38f3382d,0x38cc37ac,0x3a4939a8,0x3a6739a8,0x3b453ad3,0x3b7f3b05,0x3bd93b9d,0x3bfb3bd1,0x3bfe3bfa,0x3bd23bfb,
0x3bfc3bdd,0x3bc83b6e,0x3bdf3bfd,0x3bfd3bf8,0x3b4c3ba4,0x3b853bd6,0x3a4d3ad9,0x3a6b3b0b,0x38ee39a8,0x38c739a8,0x368d3822,0x35763796,0x31b634bd,0x2b43326f,0xac062b75,0xb371adb0,
0x340e364e,0x36a43887,0xa94d2edc,0x2d333408,0xb552b20d,0xb432ade2,0xb8c1b780,0xb899b6cc,0xba6fb9a8,0xba8cb9a8,0xbb8bbb11,0xbbb8bb3e,0xbbfebbdb,0xbbf9bbf7,0xbbbdbbf4,0xbb47bbbe,
0xbbb2bb46,0xbb35ba7c,0xbbffbbf0,0xbbf6bbb4,0xbb92bbe0,0xbbbdbbf9,0xba73bb17,0xba90bb43,0xb8bcb9a8,0xb894b9a8,0xb52fb76a,0xb40eb6b5,0xa6adb1aa,0x2e2dad1a,0x34633004,0x36f43451,
0xb4b7b705,0xb742b8d8,0x217fb099,0xaf27b499,0x350b3147,0x33d32c51,0x38b73753,0x388e369e,0x3a7639a8,0x3a9339a8,0x3b983b1d,0x3bc23b49,0x3c003be4,0x3bf33bfb,0x3ba53beb,0x3b213baa,
0x3b983b1a,0x3b0d3a3f,0x3c003be5,0x3bef3b9e,0x3b9e3be8,0x3bc63bfd,0x3a7a3b22,0x3a973b4e,0x38b239a8,0x388939a8,0x34e7373d,0x33893687,0x9cb630e4,0xb0102b11,0xb50bb12e,0xb790b4e1,
0x355e37b7,0x37dd3927,0x251b31c3,0x308d3529,0xb4c3b080,0xb340a97f,0xb8adb726,0xb884b670,0xba7eb9a8,0xba9bb9a8,0xbba3bb28,0xbbcbbb53,0xbc00bbec,0xbbebbbfe,0xbb89bbdf,0xbaf7bb93,
0xbb7abae9,0xbae1b9fe,0xbbffbbd7,0xbbe6bb86,0xbba9bbef,0xbbcfbbff,0xba81bb2e,0xba9ebb58,0xb8a8b9a8,0xb87fb9a8,0xb49fb710,0xb2f7b659,0x2884b01d,0x3109a7da,0x35b13257,0x38153570,
0xb602b832,0xb83ab972,0xaa7ab2ea,0xb185b5b6,0x347b2f72,0x32ad24b6,0x38a336f9,0x387a3642,0x3a8539a8,0x3aa239a8,0x3bae3b33,0x3bd33b5d,0x3bfd3bf2,0x3be13c00,0x3b6a3bd0,0x3acb3b79,
0x3b593ab5,0x3ab339ba,0x3bfc3bc7,0x3bdc3b6b,0x3bb33bf5,0x3bd73c00,0x3a893b39,0x3aa53b62,0x389e39a8,0x387439a8,0x345736e3,0x3263362b,0xac382eaa,0xb2011e48,0xb654b37d,0xb85fb5fd,
0xb99ab997,0xb89fb873,0xb99eb99c,0xb8f5b8ca,0xb9a3b9a0,0xb947b91e,0xb9a7b9a5,0xb995b96e,0xb9abb9a9,0xb9e0b9bb,0xb9b0b9ae,0xba26ba03,0xb9b4b9b2,0xba68ba48,0xb9b9b9b7,0xbaa6ba88,
0xb9d3b9d9,0xba9fbac0,0xb9c6b9cc,0xba59ba7d,0xb9b9b9bf,0xba0eba34,0xb9abb9b2,0xb9bdb9e6,0xb99eb9a5,0xb967b993,0xb991b997,0xb90db93b,0xb983b98a,0xb8aeb8de,0xb975b97c,0xb84cb87e,
0x395e3953,0x385c3824,0x3975396a,0x38c83892,0x398c3981,0x392f38fc,0x39a33997,0x39913961,0x39b939ae,0x39ec39bf,0x39cf39c4,0x3a423a18,0x39e439d9,0x3a913a6a,0x39f939ef,0x3ad93ab6,
0x3a0a3a18,0x3acb3af0,0x39ec39fb,0x3a7b3aa4,0x39cf39de,0x3a223a4f,0x39b039bf,0x39c139f3,0x399139a0,0x395a398e,0x39713981,0x38eb3923,0x39503961,0x387638b1,0x392f3940,0x37f63839,
0xb921b90b,0xb816b7a4,0xb94bb936,0xb89ab859,0xb975b961,0xb917b8d9,0xb99eb98a,0xb98cb953,0xb9c6b9b2,0xb9f9b9c4,0xb9ecb9d9,0xba5dba2c,0xba12b9ff,0xbab7ba8b,0xba36ba24,0xbb07bae1,
0xba3eba53,0xbaf5bb1d,0xba12ba28,0xba9bbaca,0xb9e4b9fb,0xba36ba6a,0xb9b4b9cc,0xb9c6b9ff,0xb983b99c,0xb94bb98a,0xb950b96a,0xb8c8b90b,0xb91cb936,0xb83cb883,0xb8e6b901,0xb750b7e6,
0x38e138c0,0x379e36fc,0x39213901,0x386b381e,0x395e3940,0x38fe38b6,0x399a397c,0x39883944,0x39d339b7,0x3a0539c8,0x3a0a39ef,0x3a773a40,0x3a3e3a24,0x3adc3aab,0x3a703a57,0x3b333b09,
0x3a703a8b,0x3b1c3b47,0x3a363a53,0x3abb3aed,0x39f93a18,0x3a4a3a84,0x39b939d9,0x39ca3a0c,0x39753997,0x393d3985,0x392f3953,0x38a438f2,0x38e6390b,0x38003854,0x389a38c0,0x36a73756,
0xb70db651,0xb4aeb309,0xb83cb7c5,0xb6ebb5d1,0xb8e6b892,0xb880b7fb,0xb983b936,0xb971b8fc,0xba12b9cc,0xba42b9de,0xba91ba53,0xbaefba9d,0xbafebaca,0xbb74bb37,0xbb5abb2e,0xbbcebba6,
0xbb40bb6c,0xbbb2bbd8,0xbad9bb0f,0xbb43bb80,0xba5dba9d,0xbaa6bafa,0xb9cfba18,0xb9e0ba48,0xb92fb981,0xb8f5b96e,0xb880b8d9,0xb7d5b873,0xb788b824,0xb590b6b8,0xb5fab6c3,0xb251b460,
0x367935a2,0x34113197,0x380b374b,0x3684354f,0x38cd386e,0x386637af,0x397e3928,0x396c38ed,0x3a1e39d1,0x3a4e39e2,0x3aa93a66,0x3b043aaf,0x3b1f3ae7,0x3b8c3b4e,0x3b7d3b51,0x3be03bbd,
0x3b613b8d,0x3bc73be8,0x3af53b2e,0x3b5a3b97,0x3a703ab6,0x3ab73b0f,0x39d33a24,0x39e43a53,0x3921397c,0x38e6396a,0x385c38c0,0x37883859,0x370d37e6,0x350e3651,0x3549362e,0x30de3383,
0xb5e2b4f0,0xb2e4b023,0xb7b4b6cf,0xb61db4cc,0xb8b4b849,0xb84cb761,0xb97ab919,0xb967b8de,0xba2ab9d5,0xba59b9e6,0xbac1ba79,0xbb19bac0,0xbb3dbb03,0xbba2bb65,0xbb9cbb70,0xbbefbbd0,
0xbb7fbbaa,0xbbd8bbf4,0xbb10bb4c,0xbb6fbbac,0xba82bacd,0xbac8bb23,0xb9d7ba30,0xb9e8ba5f,0xb912b978,0xb8d7b965,0xb836b8a7,0xb73ab83e,0xb690b783,0xb48ab5e8,0xb496b596,0xaecfb244,
0x3549343b,0x31a42d58,0x37503651,0x35b33447,0x389a3824,0x38313713,0x3975390b,0x396338cf,0x3a3639d9,0x3a6539ea,0x3ad93a8b,0x3b2d3ad0,0x3b5a3b1d,0x3bb53b7a,0x3bb73b8d,0x3bf93be0,
0x3b9a3bc3,0x3be73bfc,0x3b2a3b67,0x3b833bbe,0x3a943ae4,0x3ad93b37,0x39db3a3c,0x39ec3a6a,0x39033973,0x38c83961,0x3811388d,0x36eb3824,0x3611371e,0x3405357e,0x33c034fc,0x2bc03103,
0xb061a8cf,0x25b230ac,0xb549b383,0xb32eae84,0xb816b6c3,0xb750b57e,0xb95eb8c0,0xb94bb883,0xba70b9ef,0xba9bb9ff,0xbb40bae1,0xbb83bb1d,0xbbc7bb8d,0xbbf5bbcc,0xbbffbbed,0xbbeabbff,
0xbbf2bc00,0xbbfebbe3,0xbb96bbcf,0xbbd2bbf9,0xbae9bb49,0xbb25bb8b,0xb9f1ba75,0xba01baa1,0xb8b9b95c,0xb87bb949,0xb69bb809,0xb555b734,0xb2fdb514,0xad71b2bf,0xa376af7e,0x31662966,
0x2e39a052,0xabf2b21f,0x34de3276,0x32512c5e,0x37f63673,0x3718352c,0x395a38b1,0x39473873,0x3a7b39f3,0x3aa63a03,0x3b523af0,0x3b923b2c,0x3bd63b9f,0x3bfb3bd8,0x3c003bf6,0x3bda3bfc,
0x3bfa3bff,0x3bf93bd1,0x3ba73bdd,0x3bdd3bfd,0x3af83b5b,0x3b333b99,0x39f53a80,0x3a053aab,0x38a93957,0x386b3944,0x364b37db,0x350236fc,0x31ee34a8,0x2a9331e2,0xa8062cf4,0xb2d8ad3f,
0xab5c2af8,0x2e843390,0xb472b166,0xb172a86b,0xb7bfb622,0xb6e0b4d8,0xb955b8a2,0xb942b863,0xba86b9f7,0xbab0ba08,0xbb64bb00,0xbba0bb39,0xbbe3bbaf,0xbbffbbe2,0xbbfdbbfd,0xbbc6bbf5,
0xbbffbbfa,0xbbf1bbba,0xbbb7bbe8,0xbbe7bc00,0xbb07bb6c,0xbb40bba6,0xb9f9ba8b,0xba0abab6,0xb89ab953,0xb85cb940,0xb5fab7a4,0xb4aeb6c3,0xb0deb43b,0xa484b103,0x2cf4a8cf,0x34232fc9,
0x2484ae6b,0xb086b47e,0x34053055,0x30931248,0x378835d1,0x36a73484,0x39503892,0x393d3854,0x3a9139fb,0x3abb3a0c,0x3b743b0f,0x3bad3b47,0x3bed3bbe,0x3c003beb,0x3bf63c00,0x3bae3beb,
0x3c003bf0,0x3be53ba0,0x3bc53bf2,0x3bef3c00,0x3b163b7c,0x3b4d3bb3,0x39fd3a96,0x3a0e3ac0,0x388b394e,0x384c393b,0x35a8376c,0x345a368a,0x2f97339c,0xa4203023,0xafe298b6,0xb4d8b128,
0x31c93531,0x355b37e0,0xaf652839,0x9d7f315a,0xb66db42f,0xb584b1b0,0xb939b844,0xb925b803,0xbac5ba10,0xbaecba20,0xbbb9bb53,0xbbdfbb82,0xbbffbbf2,0xbbe3bc00,0xbb91bbde,0xbaf7bb8a,
0xbbd6bb81,0xbb7cbadf,0xbbf5bbfd,0xbc00bbdd,0xbb5abbbe,0xbb88bbe3,0xba12baca,0xba22baf0,0xb83cb936,0xb7f6b923,0xb405b651,0xb15ab567,0x2a61ae84,0x31e22052,0x358a3269,0x381935a8,
0xb309b5e2,0xb5f4b841,0x2da3ac44,0xa5b2b269,0x363433b4,0x35493103,0x39343834,0x392137e6,0x3acf3a14,0x3af53a24,0x3bc43b60,0x3be73b8d,0x3bfb3bf8,0x3bd63bff,0x3b703bce,0x3ac63b6d,
0x3bc53b5f,0x3b5d3aad,0x3bfa3bf9,0x3bff3bcf,0x3b663bc9,0x3b923bea,0x3a163ad4,0x3a263afa,0x382c3931,0x37d5391e,0x335f3617,0x30ac352c,0xad582cc2,0xb2f0a89d,0xb63ab3a8,0xb869b63f,
0x34233690,0x368a3890,0xabc02e6b,0x2a613377,0xb5fab309,0xb50eb055,0xb92fb824,0xb91cb7c5,0xbad9ba18,0xbafeba28,0xbbcebb6c,0xbbedbb97,0xbbf6bbfc,0xbbc7bbfd,0xbb4cbbba,0xba93bb4d,
0xbbafbb38,0xbb3cba77,0xbbfebbf2,0xbbfcbbbf,0xbb72bbd3,0xbb9cbbf0,0xba1abadd,0xba2abb03,0xb81cb92d,0xb7b4b919,0xb2b3b5dc,0xaffbb4f0,0x2f7ea9fd,0x33fd2c12,0x36e53472,0x38b636d4,
0xb4c0b73a,0xb71eb8dc,0x2839b048,0xacf4b441,0x35bf325d,0x34d22f4c,0x392a3813,0x391737a4,0x3ae23a1c,0x3b073a2c,0x3bd73b77,0x3bf33ba1,0x3bee3bff,0x3bb63bfa,0x3b233ba4,0x3a5b3b2a,
0x3b973b0d,0x3b183a3e,0x3c003be9,0x3bf73bad,0x3b7d3bdb,0x3ba63bf5,0x3a1e3ae7,0x3a2e3b0c,0x380b3928,0x37933914,0x320735a2,0x2e9d34b4,0xb0d124e9,0xb484add5,0xb78eb50e,0xb901b767,
0xb97239ba,0x39dc3996,0xb8323ab5,0x3ad0385d,0x3927b9fe,0xba1fb94d,0x37b7bae9,0xbb02b807,0xb8d83a3f,0x3a5e3900,0xb7053b1a,0x3b30375e,0x3887ba7c,0xba99b8b0,0x364ebb46,0xbb5ab6aa,
0xb90039dc,0x3a3f3972,0xad7e3be6,0x3bf83115,0x3807ba99,0xbae9b887,0xabd9bc00,0xbbfca248,0xb5f13b30,0x3b6e3705,0x32a13bed,0x3bd4b04e,0x3365bba0,0xbbc9b4d5,0xb593bbaf,0xbb803475,
0xb88739fe,0x3a99394d,0x35f13bbc,0x3b6eb414,0x3593bb1a,0xbb80b75e,0xb8b0bb02,0xba7c37b7,0xaf0e3bc9,0x3bf43365,0x3a1f39dc,0x3927b972,0xb04ebc00,0xbbed2248,0xbb30b85d,0xb7053ab5,
0xb8073a1f,0x3ae93927,0x39fe3a3f,0x394db900,0x31dbbb80,0xbbddb593,0xbb6eb832,0xb5f13ad0,0x31153c00,0x3be62248,0x3bff32a1,0x28b6bbd4,0xb7b7bb91,0xbb023534,0xbba0304e,0x34d53bed,
0xb7053a3f,0x3b303900,0x3bbc375e,0x3414bb1a,0x2248bbc9,0xbc00b365,0xbbdda8b6,0x31db3bff,0x36aa3bd4,0x3b46b2a1,0x3a7cb64e,0xb8b0bb5a,0xba1fba5e,0xb92738d8,0xb7b739fe,0x3b02394d,
0xb5f13a5e,0x3b6e38d8,0x3bd42bd9,0xb2a1bbfc,0xb115bbf4,0xbbe6af0e,0xb9dc375e,0x39723b1a,0x39273b46,0x3a1fb6aa,0x3475bad0,0xbbafb832,0xbb91b887,0xb5343a99,0x34143c00,0x3bbc2248,
0xb4d53a7c,0x3ba038b0,0x3a3fb593,0xb900bb80,0xb534bc00,0xbb912248,0xb4143ab5,0x3bbc385d,0x3a993a5e,0x3887b8d8,0xb5f1bbfc,0xbb6e2bd9,0xbbffb475,0x28b63baf,0x3ad03a1f,0x3832b927,
0xb3653a99,0x3bc93887,0x36aab996,0xbb46b9ba,0xb7b7bbed,0xbb02304e,0x34d53bfc,0x3ba02bd9,0x3b913927,0x3534ba1f,0xbae9ba3f,0xb8073900,0xbb5a28b6,0x364e3bff,0x3bd43115,0xb2a1bbe6,
0xb1153ab5,0x3be6385d,0xa8b6bb6e,0xbbffb5f1,0xb900bbbc,0xba3f3414,0x3a1f3b30,0x3927b705,0x3bfc375e,0x2bd9bb1a,0xbbedb475,0x304e3baf,0xb9ba3593,0x39963b80,0x3887b832,0xba99bad0,
0xad7e3ad0,0x3bf83832,0xb7b7bbff,0xbb0228b6,0xb9febb6e,0xb94d35f1,0x3bed3887,0x304eba99,0x3bd43414,0xb2a1bbbc,0xb9963534,0x39ba3b91,0xb6aa3900,0x3b463a3f,0xb115bba0,0xbbe6b4d5,
0xa2483ae9,0x3c003807,0xba99bb30,0xb8873705,0xbad0bb02,0xb83237b7,0x3b462d7e,0xb6aabbf8,0x3b1a28b6,0xb75ebbff,0xaf0e3a7c,0x3bf438b0,0xabd93ab5,0x3bfc385d,0xba5ebb5a,0xb8d8364e,
0x2bd93b02,0x3bfc37b7,0xbbedb927,0xb04e3a1f,0xbb6eba7c,0xb5f138b0,0x385db6aa,0xbab5bb46,0x39dcb1db,0xb972bbdd,0x38323c00,0x3ad02248,0x34d53bbc,0x3ba03414,0xbbf4b705,0x2f0e3b30,
0x304e3b1a,0x3bed375e,0xbb91b475,0x35343baf,0xbbd4b9dc,0xb2a13972,0x2248ba7c,0xbc00b8b0,0x3832b64e,0xbad0bb5a,0x3b803a99,0x3593b887,0x39003bfc,0x3a3fabd9,0xb9273414,0x3a1f3bbc,
0x32a13b30,0x3bd43705,0xb996304e,0x39ba3bed,0xbbffb927,0xa8b63a1f,0xb832bbf4,0xbad0af0e,0x3475b8b0,0xbbafba7c,0x3ba03593,0xb4d5bb80,0x3ae93b6e,0x3807b5f1,0x2bd93a99,0x3bfc3887,
0x34753b46,0x3baf36aa,0xb4d53832,0x3ba03ad0,0xbbedb85d,0x304e3ab5,0xbb30bb5a,0xb705364e,0x2248b9fe,0xbc00b94d,0x3887b414,0xba99bbbc,0x3be63a1f,0x3115b927,0x39dc3bf4,0x3972af0e,
0x35933b5a,0x3b80364e,0x31153a99,0x3be63887,0xbba0b705,0x34d53b30,0xbbf4b8d8,0x2f0e3a5e,0xb414bb02,0xbbbcb7b7,0xabd9ba1f,0xbbfcb927,0x3bd43832,0xb2a1bad0,0x3c003972,0xa248b9dc,
0x36aa3b6e,0x3b4635f1,0x38b03bdd,0x3a7c31db,0xbb1ab534,0x375e3b91,0xba3fb04e,0x39003bed,0xb807bbaf,0xbae9b475,0xb94dbbf8,0xb9fead7e,0x3ab53365,0xb85dbbc9,0x39ba28b6,0xb996bbff,
0x37b73b80,0x3b023593,0x3b1a3bc9,0x375eb365,0xba5eb2a1,0x38d83bd4,0xb53435f1,0x3b913b6e,0xb9babbfc,0xb996abd9,0xbbddbae9,0xb1db3807,0x38b0ad7e,0xba7cbbf8,0x28b6b900,0xbbffba3f,
0x385d3b91,0x3ab53534,0x3c003a5e,0x2248b8d8,0xb972ad7e,0x39dc3bf8,0x33653a3f,0x3bc93900,0xbb02bbe6,0xb7b73115,0xbb1ab6aa,0x375e3b46,0x3414b64e,0xbbbcbb5a,0xb94dbbdd,0xb9feb1db,
0x38d83ba0,0x3a5e34d5,0x3b3037b7,0xb705bb02,0xb85d28b6,0x3ab53bff,0x39ba3be6,0x39963115,0xbbc9bb6e,0xb36535f1,0xb6aa31db,0x3b463bdd,0xaf0eb94d,0xbbf4b9fe,0xbbf8bae9,0xad7e3807,
0x394d3baf,0x39fe3475,0x38d82d7e,0xba5ebbf8,0xb64e3115,0x3b5a3be6,0x3bd43b80,0x32a1b593,0xbbffba99,0x28b63887,0x336539ba,0x3bc93996,0xb75ebae9,0xbb1ab807,0xba3fb534,0x39003b91,
0x39ba3bbc,0x39963414,0x31dbb534,0xbbddbb91,0xb3653475,0x3bc93baf,0x3b803927,0xb593ba1f,0xbba0b972,0x34d539dc,0x3a3f3be6,0x39003115,0xb9febbd4,0xb94db2a1,0xb04e35f1,0x3bed3b6e,
0x3a1f3bc9,0x39273365,0xb475b972,0xbbafb9dc,0xabd9364e,0x3bfc3b5a,0x38d831db,0xba5ebbdd,0xbab5b807,0x385d3ae9,0x3c003b30,0x2248b705,0xbb80bbf4,0xb5932f0e,0x38b03b1a,0x3a7c375e,
0x3a7c3bd4,0x38b032a1,0xb972bb5a,0xb9dcb64e,0x2f0e3807,0x3bf43ae9,0x2d7eb534,0xbbf8bb91,0xb94db4d5,0x39fe3ba0,0x3a5e37b7,0xb8d8bb02,0xbc00bb46,0x224836aa,0x3bdd3bc9,0x31dbb365,
0x3ad03bdd,0x383231db,0xbb80bc00,0xb5932248,0x347538d8,0x3baf3a5e,0xb75eb9fe,0xbb1ab94d,0xb705ad7e,0x3b303bf8,0x3414af0e,0xbbbcbbf4,0xbb6eb9dc,0x35f13972,0x3ab538b0,0xb85dba7c,
0x3b1a3be6,0x375e3115,0xbbf4bb46,0x2f0e36aa,0x37053996,0x3b3039ba,0xbae9bbd4,0xb807b2a1,0xb1db304e,0x3bdd3bed,0xb64eb94d,0xbb5ab9fe,0xb9dcb7b7,0x39723b02,0x3365ad7e,0xbbc9bbf8,
0x3b5a3bed,0x364e304e,0xbab5b94d,0x385d39fe,0x38b03a3f,0x3a7c3900,0xbbffbba0,0x28b634d5,0x2d7e3593,0x3bf83b80,0xbb02bbc9,0xb7b7b365,0xb705b1db,0x3b303bdd,0xb807b9ba,0xbae9b996,
0x3b913bf4,0x35342f0e,0xb807b4d5,0x3ae93ba0,0x39ba3ad0,0x39963832,0xba99b972,0x388739dc,0x3593385d,0x3b803ab5,0xbbe6bb6e,0x311535f1,0xad7e304e,0x3bf83bed,0xbbafbbfc,0xb475abd9,
0x3bbc3bf8,0x34142d7e,0xabd92f0e,0x3bfc3bf4,0x3a993b46,0x388736aa,0xb64eb365,0x3b5a3bc9,0x38b039ba,0x3a7c3996,0xb972b85d,0x39dc3ab5,0x34753705,0x3baf3b30,0xbb1aba5e,0x375e38d8,
0x3bdd3bfc,0x31db2bd9,0x364e3807,0x3b5a3ae9,0x3b463ba0,0x36aa34d5,0x31153475,0x3be63baf,0x3a3f3ad0,0x39003832,0xad7e28b6,0x3bf83bff,0x38d83996,0x3a5e39ba,0xb534b2a1,0x3b913bd4,
0x3bf43bff,0x2f0e28b6,0x3a1f3a7c,0x392738b0,0x3bbc3bdd,0x341431db,0x394d39ba,0x39fe3996,0x3b5a3b91,0x364e3534,0x385d38d8,0x3ab53a5e,0x3ad03b1a,0x3832375e,0x36aa37b7,0x3b463b02,
0x3bff3c00,0x28b62248,0x3bc93bd4,0x336532a1,0x3bf83bfc,0x2d7e2bd9,0x3baf3bbc,0x34753414,0x3bed3bf4,0x304e2f0e,0x3b913ba0,0x353434d5,0x3bdd3be6,0x31db3115,0x3b6e3b80,0x35f13593,
0xb5933b6e,0x3b8035f1,0xb1153bdd,0x3be631db,0x34d5bb91,0xbba0b534,0x2f0ebbed,0xbbf4b04e,0xb4143baf,0x3bbc3475,0xabd93bf8,0x3bfc2d7e,0x32a1bbc9,0xbbd4b365,0x2248bbff,0xbc00a8b6,
0x37b73b46,0x3b02b6aa,0x3b1a3832,0x375ebad0,0xb8d8bab5,0xba5e385d,0xbb91b64e,0xb5343b5a,0x39ba39fe,0x3996b94d,0x3bdd3414,0x31dbbbbc,0xba7cb927,0xb8b03a1f,0xbbffaf0e,0xa8b63bf4,
0x3bd43534,0x32a1bb91,0x39bab8d8,0xb996ba5e,0xbbffad7e,0x28b63bf8,0xb8323a3f,0x3ad03900,0x3bafb115,0xb475bbe6,0x34d5bb46,0xbba0b6aa,0xbae9364e,0x38073b5a,0xabd93bdd,0x3bfc31db,
0x3a5eb75e,0xb8d8bb1a,0xb705bbaf,0xbb303475,0xb85d39dc,0x3ab53972,0x39ba3a7c,0x3996b8b0,0x3365bb5a,0xbbc9b64e,0xbb46b887,0xb6aa3a99,0x2f0e3bfc,0x3bf42bd9,0x3bf83414,0x2d7ebbbc,
0x2bd9bbaf,0xbbfcb475,0xbbedad7e,0x304e3bf8,0x35f13be6,0x3b6eb115,0x3ab5b593,0xb85dbb80,0xb9dcba99,0xb9723887,0xb83239ba,0x3ad03996,0x3ba03807,0x34d5bae9,0x2f0ebb91,0xbbf4b534,
0xb9babae9,0xb9963807,0xb1db3b30,0x3bdd3705,0x3bc937b7,0x3365bb02,0xb593bbf8,0xbb802d7e,0xbba028b6,0x34d53bff,0x3a3f3a7c,0x3900b8b0,0x394db85d,0xb9febab5,0xbbedb64e,0xb04e3b5a,
0xbbf8b365,0x2d7e3bc9,0x3b0239dc,0x37b7b972,0x39feb64e,0xb94dbb5a,0xbbedb1db,0x304e3bdd,0xb2a13ae9,0x3bd43807,0x39bab705,0xb996bb30,0xb6aabbf4,0xbb462f0e,0xb1153b1a,0x3be6375e,
0xb8b0385d,0x3a7c3ab5,0x39dcb5f1,0xb972bb6e,0xaf0ebbbc,0xbbf4b414,0xad7e3b30,0x3bf83705,0x39fe3b1a,0x394db75e,0xb8d8bbaf,0xba5e3475,0xbc00b593,0x22483b80,0x3bdd3832,0x31dbbad0,
0x33653bdd,0x3bc931db,0xb6aabc00,0xbb462248,0xbb02ba5e,0xb7b738d8,0x3ba0394d,0x34d5b9fe,0x3b912d7e,0xb534bbf8,0xbae92f0e,0x38073bf4,0xb64e3972,0x3b5a39dc,0x32a1ba7c,0xbbd4b8b0,
0x3b1a3a7c,0x375eb8b0,0xbbf4b593,0x2f0e3b80,0xbb30a248,0x37053c00,0x3807b85d,0xbae9bab5,0x31dbba5e,0xbbddb8d8,0x364e3bfc,0x3b5a2bd9,0x39723baf,0x39dcb475,0xbbc9b927,0xb3653a1f,
0x3b6e304e,0xb5f1bbed,0xb2a139fe,0x3bd4394d,0xb1153a3f,0x3be63900,0xb9dcbba0,0xb97234d5,0xba1fbb80,0xb9273593,0x3baf3365,0xb475bbc9,0x3b9131db,0xb534bbdd,0xb41439ba,0x3bbc3996,
0x3534b900,0xbb91ba3f,0x3ae93b1a,0x3807b75e,0x39ba3bc9,0x3996b365,0xba9928b6,0x38873bff,0xbb80b2a1,0x35933bd4,0xb115bb5a,0xbbe6b64e,0x2d7eba5e,0xbbf8b8d8,0x3baf39fe,0x3475b94d,
0xb807bbf8,0xbae9ad7e,0x39feaf0e,0xb94dbbf4,0x3bdd36aa,0xb1dbbb46,0x35f13bc9,0x3b6e3365,0xb11539ba,0x3be63996,0xbbffb85d,0x28b63ab5,0xbb02bb30,0xb7b73705,0x34d5b8d8,0xbba0ba5e,
0xbbddb9fe,0xb1db394d,0xb64ebbbc,0xbb5ab414,0x36aab75e,0xbb46bb1a,0x3be637b7,0xb115bb02,0x3a3f3bc9,0x3900b365,0xad7e39dc,0x3bf83972,0xba5ea248,0x38d83c00,0xbb91bab5,0xb534385d,
0xba3fa8b6,0x39003bff,0xbbf8b8b0,0x2d7e3a7c,0xb807bbdd,0xbae9b1db,0x2bd9b9ba,0xbbfcb996,0x3b6e3534,0xb5f1bb91,0x3bd43a5e,0x32a1b8d8,0x33653b1a,0x3bc9375e,0xb59337b7,0x3b803b02,
0xa8b63996,0x3bff39ba,0xb365385d,0x3bc93ab5,0xbbf8b9fe,0xad7e394d,0xbbafbae9,0xb4753807,0x304eb900,0xbbedba3f,0x3534b75e,0xbb91bb1a,0x3bdd3a7c,0x31dbb8b0,0x3b6e3b46,0x35f1b6aa,
0x39dc3c00,0x3972a248,0x3ad03bd4,0x3832b2a1,0xb9272bd9,0x3a1f3bfc,0xb7b73414,0x3b023bbc,0xba5ebbf4,0xb8d82f0e,0xbb30bba0,0xb70534d5,0x3887b115,0xba99bbe6,0x364eb593,0xbb5abb80,
0x3bf43972,0xaf0eb9dc,0x3a1f3115,0xb927bbe6,0x34143a99,0x3bbc3887,0x39fe3c00,0x394d2248,0xbb5ab705,0x364e3b30,0xb85d304e,0x3ab53bed,0xb832bba0,0xbad0b4d5,0xbb46bbaf,0xb6aa3475,
0x3887abd9,0xba99bbfc,0xb5f1bae9,0xbb6eb807,0x3b803ba0,0x3593b4d5,0x3a7c3475,0xb8b0bbaf,0xaf0e3832,0x3bf43ad0,0x3a1f3bff,0x392728b6,0xbbedb996,0x304e39ba,0xb70532a1,0x3b303bd4,
0xb414ba1f,0xbbbcb927,0xbbfcba3f,0x2bd93900,0x3a993593,0xb887bb80,0xb64ebad0,0xbb5ab832,0x3a7c3c00,0x38b02248,0x39dc32a1,0xb972bbd4,0xb4753534,0x3baf3b91,0x3b1a3bed,0x375eb04e,
0xbb30bbf4,0xb7052f0e,0xb41434d5,0x3bbc3ba0,0x2248b832,0xbc00bad0,0xbbddb9dc,0x31db3972,0x3b46385d,0xb6aabab5,0xb8b0bb6e,0xba7cb5f1,0x3a1f3bed,0x3927304e,0x37b7abd9,0xbb02bbfc,
0xbb5ab8d8,0x364e3a5e,0x3ab53bfc,0x385d2bd9,0xba7cbbf4,0xb8b0af0e,0xa8b6375e,0x3bff3b1a,0x2d7eb6aa,0xbbf8bb46,0xbb02b832,0x37b73ad0,0x3b303887,0xb705ba99,0xbae9bc00,0xb807a248,
0xb4d53115,0x3ba03be6,0x3a3f36aa,0xb900bb46,0xbb91b996,0x353439ba,0x3bbc3bd4,0x3414b2a1,0xba99bbed,0xb887b04e,0x35f139fe,0x3b6e394d,0xa8b6b7b7,0xbbffbb02,0xb832ad7e,0x3ad03bf8,
0x38323a99,0x3ad03887,0xb593b996,0xbb80b9ba,0xb475304e,0x3baf3bed,0x375e2bd9,0xbb1abbfc,0xbb30b927,0x37053a1f,0x3bbc3a3f,0xb414b900,0xbb6ebbff,0xb5f128b6,0x3ab53be6,0x385d3115,
0x3be63bd4,0x3115b2a1,0xbbffbb5a,0x28b6364e,0x39003ae9,0x3a3f3807,0xba1fbb91,0xb927b534,0xabd934d5,0x3bfc3ba0,0xb04eb7b7,0xbbedbb02,0xb9bab6aa,0x39963b46,0x38873365,0xba99bbc9,
0x3a1f3832,0xb927bad0,0xb47528b6,0x3baf3bff,0x3bfc3b6e,0xabd9b5f1,0xba5eb887,0x38d83a99,0x3ab53bbc,0x385d3414,0xbc00bb91,0x22483534,0x35933900,0x3b803a3f,0xba7cbba0,0xb8b0b4d5,
0x2248b414,0xbc00bbbc,0x3a993b91,0x38873534,0x38323475,0xbad0bbaf,0x36aa3927,0x3b463a1f,0x3b1a39dc,0xb75eb972,0xaf0e3115,0x3bf43be6,0x3bfc3bd4,0x2bd9b2a1,0xb8d8b5f1,0x3a5e3b6e,
0xb9febb02,0xb94db7b7,0x3a5e3927,0xb8d8ba1f,0xb64eb8b0,0xbb5aba7c,0x3bd43b46,0xb2a1b6aa,0x28b6b1db,0xbbffbbdd,0x3bc93c00,0x33652248,0x375e3414,0xbb1abbbc,0x3a3f3b30,0x39003705,
0xbbedbba0,0x304e34d5,0xb534b7b7,0xbb91bb02,0xbbd4bbff,0xb2a1a8b6,0x2248b115,0xbc00bbe6,0xbad0bb6e,0xb832b5f1,0x359331db,0xbb80bbdd,0xb900b9fe,0xba3fb94d,0x39273807,0xba1fbae9,
0xb85db705,0x3ab53b30,0xbc00bbed,0x2248304e,0xb9dcb927,0x39723a1f,0xbbc9bbf4,0xb365af0e,0xbb02ba7c,0x37b738b0,0xbb1abb80,0xb75eb593,0xbbbcbb6e,0x341435f1,0xb9feba99,0xb94db887,
0x34753593,0x3baf3b80,0xb4d5b365,0x3ba03bc9,0x304e32a1,0x3bed3bd4,0xb705b5f1,0x3b303b6e,0xa2482bd9,0x3c003bfc,0xb887b807,0x3a993ae9,0xb115ad7e,0x3be63bf8,0xb972b900,0x39dc3a3f,
0x3b463b5a,0x36aa364e,0x3a7c3a99,0x38b03887,0x3b1a3b30,0x375e3705,0x3a3f3a5e,0x390038d8,0x3ae93b02,0x380737b7,0x39fe3a1f,0x394d3927,0x3ab53ad0,0x385d3832,0x39ba39dc,0x39963972,
0x28b63c00,0x3bffa248,0x33653bd4,0x3bc9b2a1,0xad7ebbfc,0xbbf82bd9,0xb475bbbc,0xbbaf3414,0x304e3bf4,0x3bedaf0e,0x35343ba0,0x3b91b4d5,0xb1dbbbe6,0xbbdd3115,0xb5f1bb80,0xbb6e3593,
0x3bf4a8b6,0xaf0ebbff,0x3a1fb8b0,0xb927ba7c,0xbbbc31db,0x34143bdd,0xb94d3996,0x39fe39ba,0x3b5ab534,0xb64ebb91,0x385dba5e,0xbab5b8d8,0xbad0375e,0x38323b1a,0xb6aa3b02,0x3b4637b7,
0xb1dbbbfc,0xbbdd2bd9,0xbb5ab807,0xb64e3ae9,0x36aa3ba0,0x3b46b4d5,0x3be63475,0x3115bbaf,0xb900bad0,0xba3f3832,0xbbf8a8b6,0x2d7e3bff,0x3a5e3996,0x38d8b9ba,0x3b91b2a1,0xb534bbd4,
0xbbbc2d7e,0x34143bf8,0x2bd93bf4,0x3bfc2f0e,0x3a99b6aa,0xb887bb46,0xb64ebbc9,0xbb5a3365,0xb8b03996,0x3a7c39ba,0x39723ab5,0x39dcb85d,0x3475bb30,0xbbafb705,0xbb1ab8d8,0xb75e3a5e,
0x35343bf4,0x3b91af0e,0x3ae9b4d5,0xb807bba0,0xb996bad0,0xb9ba3832,0xb8873972,0x3a9939dc,0x3b80385d,0x3593bab5,0x3115bb6e,0xbbe6b5f1,0xbbf8b04e,0x2d7e3bed,0x34753bfc,0x3bafabd9,
0x3b5ab04e,0xb64ebbed,0xbab5b9fe,0xb85d394d,0xb8b03900,0x3a7c3a3f,0x3bff34d5,0x28b6bba0,0x2d7ebb80,0xbbf8b593,0xbb023365,0x37b73bc9,0x37053bdd,0x3b30b1db,0x3807b996,0xbae9b9ba,
0xb75ebbe6,0xbb1a3115,0xaf0e3b46,0x3bf436aa,0x3b303996,0x3705b9ba,0xb807bbd4,0xbae932a1,0xbbddb04e,0x31db3bed,0x3b5a394d,0x364eb9fe,0x3972b7b7,0xb9dcbb02,0xbbc9ad7e,0x33653bf8,
0xbad031db,0x38323bdd,0x3b802248,0xb593bc00,0x3475ba5e,0xbbafb8d8,0xb75e394d,0x3b1a39fe,0x37053bf8,0x3b30ad7e,0xb414bbf4,0xbbbcaf0e,0xbb6eb972,0xb5f139dc,0x3ab53a7c,0x385db8b0,
0x38b03bd4,0x3a7cb2a1,0xb9dcbb5a,0xb972364e,0xbbf4b807,0xaf0e3ae9,0x3bf83534,0xad7ebb91,0x39feb4d5,0xb94dbba0,0xb8d837b7,0x3a5e3b02,0xa2483b46,0x3c0036aa,0xb1dbbbc9,0xbbddb365,
0x3a1fb365,0xb927bbc9,0xb47539dc,0x3baf3972,0x2bd93b5a,0x3bfc364e,0xb8d8bbdd,0xba5e31db,0xbab5bae9,0xb85d3807,0x3c003705,0xa248bb30,0x3b802f0e,0xb593bbf4,0xb8b0375e,0x3a7c3b1a,
0xb996bbbc,0xb9ba3414,0x3bdd3534,0xb1dbbb91,0x3bc93475,0xb365bbaf,0xb5933927,0x3b803a1f,0xb4d53972,0x3ba039dc,0xb900bbe6,0xba3f3115,0xb94dbbd4,0xb9fe32a1,0x3bed35f1,0xb04ebb6e,
0xb94d3475,0x39fe3baf,0xb8d8bbf8,0xba5e2d7e,0xb64ebbe6,0xbb5ab115,0x3bd43593,0xb2a1bb80,0x3bff3887,0x28b6ba99,0xb3653996,0x3bc939ba,0xb75e3807,0x3b1a3ae9,0xba3fbb91,0xb9003534,
0x3a5e3ba0,0x38d8b4d5,0xb70537b7,0x3b303b02,0xbab5a8b6,0x385d3bff,0xb996bbe6,0xb9ba3115,0xb365bb6e,0xbbc9b5f1,0x3b4631db,0xb6aabbdd,0x3bf4394d,0x2f0eb9fe,0x2d7e3ae9,0x3bf83807,
0x385db534,0xbab5bb91,0x3c0038d8,0xa248ba5e,0x39723bf8,0x39dcad7e,0xb3653900,0x3bc93a3f,0xbb02b115,0x37b73be6,0xbb1abb46,0xb75e36aa,0xb414bb5a,0xbbbcb64e,0x394db1db,0xb9febbdd,
0xbb02bb80,0xb7b73593,0xb75ebbc9,0xbb1ab365,0x38d8b2a1,0xba5ebbd4,0x3b9135f1,0xb534bb6e,0x39963bfc,0x39baabd9,0x31db3ae9,0x3bdd3807,0xba7cad7e,0x38b03bf8,0xbbffb900,0x28b63a3f,
0xb6aa35f1,0x3b463b6e,0xb8b031db,0x3a7c3bdd,0xbb1abb91,0xb75e3534,0xba3fbbed,0xb900304e,0x3807b475,0xbae9bbaf,0x394dad7e,0xb9febbf8,0x3ab53bc9,0x385db365,0x39ba3bff,0x3996a8b6,
0x3b803b5a,0x3593b64e,0x3be63a99,0x3115b887,0xb4d53705,0x3ba03b30,0xaf0e38d8,0x3bf43a5e,0xbbbcbb02,0xb41437b7,0xbbfcba1f,0xabd93927,0x32a1b832,0xbbd4bad0,0x2248b972,0xbc00b9dc,
0x3475b6aa,0xbbafbb46,0xb4d5bad0,0xbba0b832,0x3bed3ab5,0x304eb85d,0x3b30364e,0xb705bb5a,0x2248394d,0x3c0039fe,0x38873bbc,0x3a993414,0xbbe6b927,0x31153a1f,0xb9dcaf0e,0x39723bf4,
0xbbd4bb30,0xb2a13705,0xb9bab04e,0x39963bed,0xa8b6b927,0xbbffba1f,0xbad0bbf4,0xb8322f0e,0x3baf38b0,0xb475ba7c,0x34d5b593,0xbba0bb80,0x38073b6e,0x3ae935f1,0x3bfc3a99,0x2bd9b887,
0xb04e375e,0x3bed3b1a,0x3b913baf,0x3534b475,0xbbd4b972,0x32a139dc,0x224838b0,0x3c003a7c,0xb832bb5a,0xbad0b64e,0xbb80b887,0x35933a99,0x39002bd9,0xba3fbbfc,0xb927bbbc,0xba1fb414,
0x3bfc3b02,0x2bd9b7b7,0xb04eb927,0xbbedba1f,0x35f13a7c,0x3b6e38b0,0x3ab536aa,0xb85dbb46,0xb972b1db,0x39dc3bdd,0x3ad03c00,0x3832a248,0xbba0bbbc,0xb4d53414,0xaf0e3705,0x3bf43b30,
0xa248b807,0xbc00bae9,0xba99b705,0x38873b30,0x3ad037b7,0xb832bb02,0xbb46bbf8,0xb6aa2d7e,0x3b1a3bff,0x375ea8b6,0xaf0eb8b0,0xbbf4ba7c,0x2bd9385d,0x3bfc3ab5,0x3a5e364e,0xb8d8bb5a,
0xbbf8bad0,0x2d7e3832,0x3b023bff,0x37b728b6,0xb94dbb6e,0xb9feb5f1,0x304e3887,0x3bed3a99,0x32a1b414,0xbbd4bbbc,0xb9bab534,0x39963b91,0x3b463900,0xb6aaba3f,0xbbe6bba0,0xb11534d5,
0x3115385d,0x3be63ab5,0x28b6b5f1,0xbbffbb6e,0xb900b414,0x3a3f3bbc,0x3a1f3705,0xb927bb30,0xbbfcbb1a,0x2bd9375e,0x3bed3baf,0x304eb475,0xb9babb80,0xb996b593,0x38873ad0,0x3a993832,
0x3bc93a99,0xb365b887,0xbb46b996,0x36aa39ba,0x3b023bed,0x37b7304e,0xbba0bbfc,0xb4d52bd9,0x35343927,0x3b913a1f,0xb807ba3f,0xbae9b900,0xb64ea8b6,0x3b5a3bff,0x32a1b115,0xbbd4bbe6,
0xb4d5b8b0,0xbba0ba7c,0x3a3f3b80,0x39003593,0x35342248,0xbb91bc00,0x3414385d,0x3bbc3ab5,0x3a9938d8,0xb887ba5e,0xb5f1abd9,0x3b6e3bfc,0x3bff3baf,0x28b6b475,0xbad0b927,0x38323a1f,
0xbb6eba5e,0x35f138d8,0x32a1abd9,0xbbd4bbfc,0xbbe6bbf4,0xb1152f0e,0x3972375e,0xb9dcbb1a,0xba1fbb46,0xb927b6aa,0x3baf3ad0,0xb475b832,0xb534b887,0xbb91ba99,0x3bbc3c00,0x3414a248,
0x37053900,0x3b303a3f,0xbbbcbb1a,0x3414375e,0x22483365,0x3c003bc9,0xbbddbbff,0xb1db28b6,0xb6aab2a1,0x3b463bd4,0xba7cbb5a,0xb8b0b64e,0xba1fb8d8,0x39273a5e,0xb7b7b94d,0xbb02b9fe,
0x3ae93a1f,0xb807b927,0x394d3a3f,0x39fe3900,0x3bdd3b80,0xb1dbb593,0x35f13832,0x3b6e3ad0,0x3be63c00,0x3115a248,0x28b632a1,0x3bff3bd4,0x3b023b91,0x37b73534,0xb4d5b04e,0x3ba03bed,
0xb887b94d,0xba99b9fe,0x35f13414,0xbb6ebbbc,0xb593b75e,0xbb80bb1a,0x38b037b7,0xba7cbb02,0xaf0eb365,0xbbf4bbc9,0x3a1f3972,0xb927b9dc,0x304e2248,0xbbedbc00,0x3b303ab5,0xb705b85d,
0xba3fb9dc,0x39003972,0xbbf8bbe6,0x2d7e3115,0xbae9ba99,0x38073887,0xbbfcbc00,0xabd92248,0xbb6ebb30,0x35f13705,0xbbd4bbed,0xb2a1b04e,0xbbc9bba0,0x336534d5,0xbb80bbaf,0xb593b475,
0x39723996,0x39dc39ba,0x3832385d,0x3ad03ab5,0x3927394d,0x3a1f39fe,0x37b73807,0x3b023ae9,0x38d83900,0x3a5e3a3f,0x3705375e,0x3b303b1a,0x388738b0,0x3a993a7c,0x364e36aa,0x3b5a3b46,
0x36aa3b5a,0x3b46b64e,0x38b03a99,0x3a7cb887,0xb75ebb30,0xbb1a3705,0xb900ba5e,0xba3f38d8,0x38073b02,0x3ae9b7b7,0x394d3a1f,0x39feb927,0xb85dbad0,0xbab53832,0xb996b9dc,0xb9ba3972,
0x3475bb80,0xbbafb593,0xb4d5bbc9,0xbba03365,0xb04e3bd4,0x3bed32a1,0x37053b6e,0x3b30b5f1,0xa248bbfc,0xbc00abd9,0xb887bae9,0xba993807,0x31153bf8,0x3be6ad7e,0x39723a3f,0x39dcb900,
0xbab53705,0x385d3b30,0xa2483bed,0x3c00304e,0x3972b927,0xb9dcba1f,0xb365bbf4,0xbbc92f0e,0xb7b73a7c,0x3b0238b0,0x375e3b80,0x3b1ab593,0x3414bb6e,0xbbbcb5f1,0xb94dba99,0xb9fe3887,
0x3bed34d5,0x304ebba0,0x3534bb02,0xbb91b7b7,0xbbd428b6,0x32a13bff,0x22483be6,0x3c003115,0x3ad0b5f1,0xb832bb6e,0xb593bbdd,0xbb8031db,0xb900394d,0x3a3f39fe,0x39273ae9,0x3a1fb807,
0xb94dbb02,0xb9fe37b7,0xb8d83927,0x3a5e3a1f,0x3b5a38b0,0x364eba7c,0x32a1bb46,0xbbd4b6aa,0xbbffb1db,0x28b63bdd,0x33653c00,0x3bc9a248,0x3b1ab414,0xb75ebbbc,0xb900bb30,0xba3f3705,
0x22483bbc,0x3c003414,0x3a99b534,0xb887bb91,0xb832bbaf,0xbad03475,0xb6aa3a1f,0x3b463927,0x3b1a3972,0x375eb9dc,0xaf0ebbe6,0xbbf4b115,0xbbfcb2a1,0x2bd93bd4,0x38d83b6e,0x3a5eb5f1,
0x3927b832,0xba1fbad0,0xbbafa8b6,0x34753bff,0xabd93b6e,0x3bfc35f1,0x38d8b887,0xba5eba99,0xb85dbbbc,0xbab53414,0xa2483b91,0x3c003534,0x3b803900,0x3593ba3f,0xb8b0bba0,0xba7c34d5,
0xbbe6b2a1,0x31153bd4,0x3bff364e,0x28b6bb5a,0x3900b807,0xba3fbae9,0xba1f3534,0x39273b91,0x2bd93ba0,0x3bfc34d5,0x304ebb02,0xbbedb7b7,0xb9babb46,0xb99636aa,0x38873bc9,0x3a99b365,
0x3ad03a99,0x3832b887,0xbb80b996,0xb59339ba,0xbbafb04e,0x34753bed,0x3b1aabd9,0xb75ebbfc,0x3705b927,0xbb30ba1f,0xb4143a3f,0x3bbc3900,0x35f13bff,0x3b6e28b6,0xb85dbbe6,0xbab53115,
0xb4d5bbe6,0xbba0b115,0x3a3f3b46,0x3900b6aa,0x3b9139ba,0x3534b996,0xbbbcb2a1,0x34143bd4,0xba99304e,0x38873bed,0x35f1b94d,0xbb6eb9fe,0x28b6bb02,0xbbffb7b7,0x38323bf8,0x3ad0ad7e,
0xb64e38d8,0x3b5a3a5e,0xb85dbbfc,0xbab52bd9,0xb8b0bbf4,0xba7c2f0e,0x3bff375e,0xa8b6bb1a,0x3bf836aa,0xad7ebb46,0xb7b73832,0x3b023ad0,0xb7053887,0x3b303a99,0xb807bc00,0xbae92248,
0x3b302f0e,0xb705bbf4,0x34143ba0,0x3bbc34d5,0x22483ad0,0x3c003832,0xbbddb972,0xb1db39dc,0xbb46bab5,0xb6aa385d,0x38b0b5f1,0xba7cbb6e,0x3a1fb04e,0xb927bbed,0x37b73bfc,0x3b022bd9,
0xbbbcba1f,0xb4143927,0x2bd9ba3f,0xbbfcb900,0x3887b593,0xba99bb80,0x3b5a3ad0,0x364eb832,0x38b03c00,0x3a7ca248,0xb97232a1,0x39dc3bd4,0xbbafb534,0x34753b91,0xb75ebbed,0xbb1ab04e,
0x38873bfc,0x3a992bd9,0xb5f13807,0x3b6e3ae9,0xbb80b4d5,0x35933ba0,0xba7cbbaf,0xb8b03475,0xaf0ebad0,0xbbf4b832,0x3a1fa8b6,0xb927bbff,0x3bed39ba,0x304eb996,0x37053bd4,0x3b3032a1,
0x2f0eb972,0xbbf4b9dc,0x3927b115,0xba1fbbe6,0x3bbc3a99,0x3414b887,0x394d3c00,0x39fea248,0xb64e3705,0x3b5a3b30,0xbab5b04e,0x385d3bed,0xbad0bba0,0xb83234d5,0xb6aabbaf,0xbb46b475,
0xb9dca248,0x39723c00,0xbad0b2a1,0x38323bd4,0xb927bbfc,0xba1fabd9,0xb7b7bbbc,0xbb02b414,0x3a5e2f0e,0xb8d8bbf4,0x3b3034d5,0xb705bba0,0x38873be6,0x3a993115,0x364e3b80,0x3b5a3593,
0x3bff3996,0xa8b6b9ba,0x3bc9385d,0xb365bab5,0x2d7e39fe,0x3bf8394d,0x34753ae9,0x3baf3807,0xbbedb900,0x304e3a3f,0xbb91b75e,0x35343b1a,0xb1dbba7c,0xbbddb8b0,0xb5f1bb46,0xbb6eb6aa,
0xba3fbbff,0xb90028b6,0xbbf8ba7c,0xad7e38b0,0x3807b1db,0xbae9bbdd,0xabd9b996,0xbbfcb9ba,0x3b6e3b91,0x35f1b534,0x3bd438d8,0xb2a1ba5e,0xb365375e,0x3bc93b1a,0x35933b02,0x3b8037b7,
0x31db39fe,0x3bdd394d,0x3b5a3bbc,0x364eb414,0xbb46b75e,0x36aa3b1a,0xb11537b7,0x3be63b02,0xb900bbc9,0xba3fb365,0xbbf8b9dc,0x2d7e3972,0x38d8a248,0xba5ebc00,0xb534bab5,0xbb91b85d,
0x3807ad7e,0xbae9bbf8,0xb9febbf4,0xb94daf0e,0x3bdd3b46,0x31dbb6aa,0x35f1b365,0xbb6ebbc9,0x31153996,0x3be639ba,0x3bff3ab5,0x28b6b85d,0xbb02b705,0x37b73b30,0x34d53a5e,0x3ba038d8,
0xbb91b900,0x35343a3f,0x38073b1a,0x3ae9375e,0xb996bbc9,0xb9bab365,0xb887a8b6,0x3a993bff,0x3593b2a1,0xbb80bbd4,0xbbe6bb5a,0xb115364e,0x3bf83a5e,0xad7eb8d8,0xb475b9fe,0xbbafb94d,
0x3b6e3bed,0x35f1b04e,0xb2a1b94d,0xbbd4b9fe,0x31153900,0x3be63a3f,0x39dc34d5,0xb972bba0,0xba1fb593,0x39273b80,0x3baf3bc9,0x3475b365,0xbb91bbdd,0xb53431db,0x34143996,0x3bbc39ba,
0xb75eba7c,0xbb1ab8b0,0xaf0e3593,0x3bf43b80,0x3705a248,0xbb30bc00,0xbae9b85d,0x38073ab5,0x3bdd3a5e,0xb1dbb8d8,0xbb5abbfc,0xb64e2bd9,0x39dc3baf,0x39723475,0xb365b927,0xbbc9ba1f,
0xb36531db,0x3bc93bdd,0x36aa2248,0xbb46bc00,0xbb02b8d8,0x37b73a5e,0x3ba039fe,0xb4d5b94d,0xbb91bbf8,0xb5342d7e,0x3ae93bf4,0x38072f0e,0xb64eb9dc,0xbb5ab972,0x32a138b0,0x3bd43a7c,
0x3a7c385d,0xb8b0bab5,0xb972b5f1,0x39dc3b6e,0x3bf43bbc,0x2f0eb414,0xbbf8bb30,0x2d7e3705,0x394d3b1a,0x39fe375e,0xba5ebbaf,0xb8d8b475,0xa2483593,0x3c003b80,0xb1dbb832,0xbbddbad0,
0xbbf8bbc9,0xad7e3365,0x3b023972,0xb7b7b9dc,0xb9febb5a,0xb94db64e,0x3bed3bdd,0x304eb1db,0xb2a1b807,0xbbd4bae9,0x39ba3b30,0x39963705,0x36aa2f0e,0xbb46bbf4,0x3115375e,0x3be63b1a,
0x39963ae9,0x39ba3807,0xbbddbb30,0x31db3705,0x336537b7,0x3bc93b02,0xbb80bbf8,0xb593ad7e,0xb4d5a8b6,0x3ba03bff,0xb900ba7c,0xba3fb8b0,0xb9feb85d,0x394d3ab5,0xb04eb64e,0xbbedbb5a,
0xabd9b475,0xbbfcbbaf,0x3bed3bf8,0x304ead7e,0x35f13115,0xbb6ebbe6,0x3ab53b80,0x385d3593,0x39dc3887,0xb972ba99,0x38323996,0x3ad039ba,0x3ba03ae9,0xb4d5b807,0x2f0e3534,0x3bf43b91,
0xb8d8b75e,0x3a5e3b1a,0xbb30bbaf,0xb705b475,0xbab5b9dc,0x385d3972,0xb996ba7c,0xb9bab8b0,0xbbc9bb5a,0x3365364e,0xb6aab887,0xbb46ba99,0xbbf4bbfc,0xaf0e2bd9,0xad7eb414,0xbbf8bbbc,
0x3bd43b91,0xb2a1b534,0x39ba3a5e,0x399638d8,0x3bff3bf8,0x28b6ad7e,0x38323900,0x3ad03a3f,0x3baf3be6,0x34753115,0x34d536aa,0x3ba03b46,0x3ae93b5a,0x3807364e,0x2bd931db,0x3bfc3bdd,
0xbb02bb46,0xb7b7b6aa,0xb75eb832,0xbb1abad0,0xba5ebab5,0xb8d8b85d,0xb534b64e,0xbb91bb5a,0xb996b9fe,0xb9bab94d,0xb1dbb414,0xbbddbbbc,0xb8b0b927,0xba7cba1f,0xa8b6af0e,0xbbffbbf4,
0x359335f1,0x3b803b6e,0x311531db,0x3be63bdd,0x34d53534,0x3ba03b91,0x2f0e304e,0x3bf43bed,0x34143475,0x3bbc3baf,0x2bd92d7e,0x3bfc3bf8,0x32a13365,0x3bd43bc9,0x224828b6,0x3c003bff,
0x40000,0x60002,0xc0008,0xe000a,0x380034,0x3a0036,0x40003c,0x42003e,0x6c0068,0x6e006a,0x740070,0x760072,0xa0009c,0xa2009e,0xa800a4,0xaa00a6,
0xd400d0,0xd600d2,0xdc00d8,0xde00da,0x1080104,0x10a0106,0x110010c,0x112010e,0x13c0138,0x13e013a,0x1440140,0x1460142,0x170016c,0x172016e,0x1780174,0x17a0176,
0x1a401a0,0x1a601a2,0x1ac01a8,0x1ae01aa,0x1d801d4,0x1da01d6,0x1e001dc,0x1e201de,0x20c0208,0x20e020a,0x2140210,0x2160212,0x240023c,0x242023e,0x2480244,0x24a0246,
0x2740270,0x2760272,0x27c0278,0x27e027a,0x2a802a4,0x2aa02a6,0x2b002ac,0x2b202ae,0x2dc02d8,0x2de02da,0x2e402e0,0x2e602e2,0x310030c,0x312030e,0x3180314,0x31a0316,
0x3440340,0x3460342,0x34c0348,0x34e034a,0x3780374,0x37a0376,0x380037c,0x382037e,0x3ac03a8,0x3ae03aa,0x3b403b0,0x3b603b2,0x3e003dc,0x3e203de,0x3e803e4,0x3ea03e6,
0x4140410,0x4160412,0x41c0418,0x41e041a,0x4480444,0x44a0446,0x450044c,0x452044e,0x47c0478,0x47e047a,0x4840480,0x4860482,0x4b004ac,0x4b204ae,0x4b804b4,0x4ba04b6,
0x4e404e0,0x4e604e2,0x4ec04e8,0x4ee04ea,0x5180514,0x51a0516,0x520051c,0x522051e,0x54c0548,0x54e054a,0x5540550,0x5560552,0x580057c,0x582057e,0x5880584,0x58a0586,
0x5b405b0,0x5b605b2,0x5bc05b8,0x5be05ba,0x5e805e4,0x5ea05e6,0x5f005ec,0x5f205ee,0x61c0618,0x61e061a,0x6240620,0x6260622,0x650064c,0x652064e,0x6580654,0x65a0656,
0x140010,0x160012,0x120010,0x440012,0x480044,0x4a0046,0x460044,0x780046,0x7c0078,0x7e007a,0x7a0078,0xac007a,0xb000ac,0xb200ae,0xae00ac,0xe000ae,
0xe400e0,0xe600e2,0xe200e0,0x11400e2,0x1180114,0x11a0116,0x1160114,0x1480116,0x14c0148,0x14e014a,0x14a0148,0x17c014a,0x180017c,0x182017e,0x17e017c,0x1b0017e,
0x1b401b0,0x1b601b2,0x1b201b0,0x1e401b2,0x1e801e4,0x1ea01e6,0x1e601e4,0x21801e6,0x21c0218,0x21e021a,0x21a0218,0x24c021a,0x250024c,0x252024e,0x24e024c,0x280024e,
0x2840280,0x2860282,0x2820280,0x2b40282,0x2b802b4,0x2ba02b6,0x2b602b4,0x2e802b6,0x2ec02e8,0x2ee02ea,0x2ea02e8,0x31c02ea,0x320031c,0x322031e,0x31e031c,0x350031e,
0x3540350,0x3560352,0x3520350,0x3840352,0x3880384,0x38a0386,0x3860384,0x3b80386,0x3bc03b8,0x3be03ba,0x3ba03b8,0x3ec03ba,0x3f003ec,0x3f203ee,0x3ee03ec,0x42003ee,
0x4240420,0x4260422,0x4220420,0x4540422,0x4580454,0x45a0456,0x4560454,0x4880456,0x48c0488,0x48e048a,0x48a0488,0x4bc048a,0x4c004bc,0x4c204be,0x4be04bc,0x4f004be,
0x4f404f0,0x4f604f2,0x4f204f0,0x52404f2,0x5280524,0x52a0526,0x5260524,0x5580526,0x55c0558,0x55e055a,0x55a0558,0x58c055a,0x590058c,0x592058e,0x58e058c,0x5c0058e,
0x5c405c0,0x5c605c2,0x5c205c0,0x5f405c2,0x5f805f4,0x5fa05f6,0x5f605f4,0x62805f6,0x62c0628,0x62e062a,0x62a0628,0x65c062a,0x660065c,0x662065e,0x65e065c,0x18065e,
0x180018,0x4c001a,0x1a0018,0x4c001a,0x4c004c,0x80004e,0x4e004c,0x80004e,0x800080,0xb40082,0x820080,0xb40082,0xb400b4,0xe800b6,0xb600b4,0xe800b6,
0xe800e8,0x11c00ea,0xea00e8,0x11c00ea,0x11c011c,0x150011e,0x11e011c,0x150011e,0x1500150,0x1840152,0x1520150,0x1840152,0x1840184,0x1b80186,0x1860184,0x1b80186,
0x1b801b8,0x1ec01ba,0x1ba01b8,0x1ec01ba,0x1ec01ec,0x22001ee,0x1ee01ec,0x22001ee,0x2200220,0x2540222,0x2220220,0x2540222,0x2540254,0x2880256,0x2560254,0x2880256,
0x2880288,0x2bc028a,0x28a0288,0x2bc028a,0x2bc02bc,0x2f002be,0x2be02bc,0x2f002be,0x2f002f0,0x32402f2,0x2f202f0,0x32402f2,0x3240324,0x3580326,0x3260324,0x3580326,
0x3580358,0x38c035a,0x35a0358,0x38c035a,0x38c038c,0x3c0038e,0x38e038c,0x3c0038e,0x3c003c0,0x3f403c2,0x3c203c0,0x3f403c2,0x3f403f4,0x42803f6,0x3f603f4,0x42803f6,
0x4280428,0x45c042a,0x42a0428,0x45c042a,0x45c045c,0x490045e,0x45e045c,0x490045e,0x4900490,0x4c40492,0x4920490,0x4c40492,0x4c404c4,0x4f804c6,0x4c604c4,0x4f804c6,
0x4f804f8,0x52c04fa,0x4fa04f8,0x52c04fa,0x52c052c,0x560052e,0x52e052c,0x560052e,0x5600560,0x5940562,0x5620560,0x5940562,0x5940594,0x5c80596,0x5960594,0x5c80596,
0x5c805c8,0x5fc05ca,0x5ca05c8,0x5fc05ca,0x5fc05fc,0x63005fe,0x5fe05fc,0x63005fe,0x6300630,0x6640632,0x6320630,0x6640632,0x6640664,0x1c0666,0x6660664,0x1c0666,
0x1c001c,0x50001e,0x1e001c,0x50001e,0x500050,0x840052,0x520050,0x840052,0x840084,0xb80086,0x860084,0xb80086,0xb800b8,0xec00ba,0xba00b8,0xec00ba,
0xec00ec,0x12000ee,0xee00ec,0x12000ee,0x1200120,0x1540122,0x1220120,0x1540122,0x1540154,0x1880156,0x1560154,0x1880156,0x1880188,0x1bc018a,0x18a0188,0x1bc018a,
0x1bc01bc,0x1f001be,0x1be01bc,0x1f001be,0x1f001f0,0x22401f2,0x1f201f0,0x22401f2,0x2240224,0x2580226,0x2260224,0x2580226,0x2580258,0x28c025a,0x25a0258,0x28c025a,
0x28c028c,0x2c0028e,0x28e028c,0x2c0028e,0x2c002c0,0x2f402c2,0x2c202c0,0x2f402c2,0x2f402f4,0x32802f6,0x2f602f4,0x32802f6,0x3280328,0x35c032a,0x32a0328,0x35c032a,
0x35c035c,0x390035e,0x35e035c,0x390035e,0x3900390,0x3c40392,0x3920390,0x3c40392,0x3c403c4,0x3f803c6,0x3c603c4,0x3f803c6,0x3f803f8,0x42c03fa,0x3fa03f8,0x42c03fa,
0x42c042c,0x460042e,0x42e042c,0x460042e,0x4600460,0x4940462,0x4620460,0x4940462,0x4940494,0x4c80496,0x4960494,0x4c80496,0x4c804c8,0x4fc04ca,0x4ca04c8,0x4fc04ca,
0x4fc04fc,0x53004fe,0x4fe04fc,0x53004fe,0x5300530,0x5640532,0x5320530,0x5640532,0x5640564,0x5980566,0x5660564,0x5980566,0x5980598,0x5cc059a,0x59a0598,0x5cc059a,
0x5cc05cc,0x60005ce,0x5ce05cc,0x60005ce,0x6000600,0x6340602,0x6020600,0x6340602,0x6340634,0x6680636,0x6360634,0x6680636,0x6680668,0x20066a,0x66a0668,0x20066a,
0x5d605d6,0x60a05d6,0x5d605d6,0x60a060a,0x60a060a,0x63e063e,0x60a060a,0x63e063e,0x63e063e,0x672063e,0x63e063e,0x6720672,0x6720672,0x280028,0x6720672,0x280028,
0x5060506,0x53a0506,0x5060506,0x53a053a,0x53a053a,0x56e056e,0x53a053a,0x56e056e,0x56e056e,0x5a2056e,0x56e056e,0x5a205a2,0x5a205a2,0x5d605d6,0x5a205a2,0x5d605d6,
0x4360436,0x46a0436,0x4360436,0x46a046a,0x46a046a,0x49e049e,0x46a046a,0x49e049e,0x49e049e,0x4d2049e,0x49e049e,0x4d204d2,0x4d204d2,0x5060506,0x4d204d2,0x5060506,
0x3660366,0x39a0366,0x3660366,0x39a039a,0x39a039a,0x3ce03ce,0x39a039a,0x3ce03ce,0x3ce03ce,0x40203ce,0x3ce03ce,0x4020402,0x4020402,0x4360436,0x4020402,0x4360436,
0x2960296,0x2ca0296,0x2960296,0x2ca02ca,0x2ca02ca,0x2fe02fe,0x2ca02ca,0x2fe02fe,0x2fe02fe,0x33202fe,0x2fe02fe,0x3320332,0x3320332,0x3660366,0x3320332,0x3660366,
0x1c601c6,0x1fa01c6,0x1c601c6,0x1fa01fa,0x1fa01fa,0x22e022e,0x1fa01fa,0x22e022e,0x22e022e,0x262022e,0x22e022e,0x2620262,0x2620262,0x2960296,0x2620262,0x2960296,
0xf600f6,0x12a00f6,0xf600f6,0x12a012a,0x12a012a,0x15e015e,0x12a012a,0x15e015e,0x15e015e,0x192015e,0x15e015e,0x1920192,0x1920192,0x1c601c6,0x1920192,0x1c601c6,
0x260026,0x5a0026,0x260026,0x5a005a,0x5a005a,0x8e008e,0x5a005a,0x8e008e,0x8e008e,0xc2008e,0x8e008e,0xc200c2,0xc200c2,0xf600f6,0xc200c2,0xf600f6,
0x5d405d4,0x60805d4,0x5d405d4,0x6080608,0x6080608,0x63c063c,0x6080608,0x63c063c,0x63c063c,0x670063c,0x63c063c,0x6700670,0x6700670,0x260026,0x6700670,0x260026,
0x5040504,0x5380504,0x5040504,0x5380538,0x5380538,0x56c056c,0x5380538,0x56c056c,0x56c056c,0x5a0056c,0x56c056c,0x5a005a0,0x5a005a0,0x5d405d4,0x5a005a0,0x5d405d4,
0x4340434,0x4680434,0x4340434,0x4680468,0x4680468,0x49c049c,0x4680468,0x49c049c,0x49c049c,0x4d0049c,0x49c049c,0x4d004d0,0x4d004d0,0x5040504,0x4d004d0,0x5040504,
0x3640364,0x3980364,0x3640364,0x3980398,0x3980398,0x3cc03cc,0x3980398,0x3cc03cc,0x3cc03cc,0x40003cc,0x3cc03cc,0x4000400,0x4000400,0x4340434,0x4000400,0x4340434,
0x2940294,0x2c80294,0x2940294,0x2c802c8,0x2c802c8,0x2fc02fc,0x2c802c8,0x2fc02fc,0x2fc02fc,0x33002fc,0x2fc02fc,0x3300330,0x3300330,0x3640364,0x3300330,0x3640364,
0x1c401c4,0x1f801c4,0x1c401c4,0x1f801f8,0x1f801f8,0x22c022c,0x1f801f8,0x22c022c,0x22c022c,0x260022c,0x22c022c,0x2600260,0x2600260,0x2940294,0x2600260,0x2940294,
0xf400f4,0x12800f4,0xf400f4,0x1280128,0x1280128,0x15c015c,0x1280128,0x15c015c,0x15c015c,0x190015c,0x15c015c,0x1900190,0x1900190,0x1c401c4,0x1900190,0x1c401c4,
0x240024,0x580024,0x240024,0x580058,0x580058,0x8c008c,0x580058,0x8c008c,0x8c008c,0xc0008c,0x8c008c,0xc000c0,0xc000c0,0xf400f4,0xc000c0,0xf400f4,
0x5d205d2,0x60605d2,0x5d205d2,0x6060606,0x6060606,0x63a063a,0x6060606,0x63a063a,0x63a063a,0x66e063a,0x63a063a,0x66e066e,0x66e066e,0x240024,0x66e066e,0x240024,
0x5020502,0x5360502,0x5020502,0x5360536,0x5360536,0x56a056a,0x5360536,0x56a056a,0x56a056a,0x59e056a,0x56a056a,0x59e059e,0x59e059e,0x5d205d2,0x59e059e,0x5d205d2,
0x4320432,0x4660432,0x4320432,0x4660466,0x4660466,0x49a049a,0x4660466,0x49a049a,0x49a049a,0x4ce049a,0x49a049a,0x4ce04ce,0x4ce04ce,0x5020502,0x4ce04ce,0x5020502,
0x3620362,0x3960362,0x3620362,0x3960396,0x3960396,0x3ca03ca,0x3960396,0x3ca03ca,0x3ca03ca,0x3fe03ca,0x3ca03ca,0x3fe03fe,0x3fe03fe,0x4320432,0x3fe03fe,0x4320432,
0x2920292,0x2c60292,0x2920292,0x2c602c6,0x2c602c6,0x2fa02fa,0x2c602c6,0x2fa02fa,0x2fa02fa,0x32e02fa,0x2fa02fa,0x32e032e,0x32e032e,0x3620362,0x32e032e,0x3620362,
0x1c201c2,0x1f601c2,0x1c201c2,0x1f601f6,0x1f601f6,0x22a022a,0x1f601f6,0x22a022a,0x22a022a,0x25e022a,0x22a022a,0x25e025e,0x25e025e,0x2920292,0x25e025e,0x2920292,
0xf200f2,0x12600f2,0xf200f2,0x1260126,0x1260126,0x15a015a,0x1260126,0x15a015a,0x15a015a,0x18e015a,0x15a015a,0x18e018e,0x18e018e,0x1c201c2,0x18e018e,0x1c201c2,
0x220022,0x560022,0x220022,0x560056,0x560056,0x8a008a,0x560056,0x8a008a,0x8a008a,0xbe008a,0x8a008a,0xbe00be,0xbe00be,0xf200f2,0xbe00be,0xf200f2,
0x5d005d0,0x60405d0,0x5d005d0,0x6040604,0x6040604,0x6380638,0x6040604,0x6380638,0x6380638,0x66c0638,0x6380638,0x66c066c,0x66c066c,0x220022,0x66c066c,0x220022,
0x5000500,0x5340500,0x5000500,0x5340534,0x5340534,0x5680568,0x5340534,0x5680568,0x5680568,0x59c0568,0x5680568,0x59c059c,0x59c059c,0x5d005d0,0x59c059c,0x5d005d0,
0x4300430,0x4640430,0x4300430,0x4640464,0x4640464,0x4980498,0x4640464,0x4980498,0x4980498,0x4cc0498,0x4980498,0x4cc04cc,0x4cc04cc,0x5000500,0x4cc04cc,0x5000500,
0x3600360,0x3940360,0x3600360,0x3940394,0x3940394,0x3c803c8,0x3940394,0x3c803c8,0x3c803c8,0x3fc03c8,0x3c803c8,0x3fc03fc,0x3fc03fc,0x4300430,0x3fc03fc,0x4300430,
0x2900290,0x2c40290,0x2900290,0x2c402c4,0x2c402c4,0x2f802f8,0x2c402c4,0x2f802f8,0x2f802f8,0x32c02f8,0x2f802f8,0x32c032c,0x32c032c,0x3600360,0x32c032c,0x3600360,
0x1c001c0,0x1f401c0,0x1c001c0,0x1f401f4,0x1f401f4,0x2280228,0x1f401f4,0x2280228,0x2280228,0x25c0228,0x2280228,0x25c025c,0x25c025c,0x2900290,0x25c025c,0x2900290,
0xf000f0,0x12400f0,0xf000f0,0x1240124,0x1240124,0x1580158,0x1240124,0x1580158,0x1580158,0x18c0158,0x1580158,0x18c018c,0x18c018c,0x1c001c0,0x18c018c,0x1c001c0,
0x200020,0x540020,0x200020,0x540054,0x540054,0x880088,0x540054,0x880088,0x880088,0xbc0088,0x880088,0xbc00bc,0xbc00bc,0xf000f0,0xbc00bc,0xf000f0,
0x30003000,0x30003000,0x30003000,0x30003000,0x30003000,0x30003000,0x30003000,0x30003000,0x0,0x0,0x0,0x0,0x0,0x0,0x0,0x0,
0x30003000,0x30003000,0x30003000,0x30003000,0x30003000,0x30003000,0x30003000,0x30003000,0x0,0x0,0x0,0x0,0x0,0x0,0x0,0x0,
0x2a1f2da8,0xaf64ada8,0xaa1fada8,0x2f642da8,0x2f643000,0xaa1f0000,0xaf64b000,0x2a1f8000,0x2f642da8,0x2a1f2da8,0xaf64ada8,0xaa1fada8,0x2a1f0000,0x2f643000,0xaa1f0000,0xaf64b000,
0x263e2c72,0xafd9aea7,0xa63eac72,0x2fd92ea7,0x2ea72fd9,0xac72a63e,0xaea7afd9,0x2c72263e,0x2fd92ea7,0x263e2c72,0xafd9aea7,0xa63eac72,0x2c72263e,0x2ea72fd9,0xac72a63e,0xaea7afd9,
0x2da80000,0xada80000,0x2da88000,0xada80000,0x2da83000,0xada8b000,0x2da83000,0xada8b000,0x2da83000,0xada8b000,0x2da83000,0xada8b000,0xada80000,0x2da88000,0xada80000,0x2da88000,
0x2f642a1f,0xaf64aa1f,0x2f642a1f,0xaf64aa1f,0x2a1f2f64,0xaa1faf64,0x2a1f2f64,0xaa1faf64,0x2a1f2f64,0xaa1faf64,0x2a1f2f64,0xaa1faf64,0xaf64aa1f,0x2f642a1f,0xaf64aa1f,0x2f642a1f,
0xaa1f2da8,0x2f642da8,0x2a1fada8,0xaf64ada8,0x2f640000,0xaa1fb000,0xaf640000,0x2a1f3000,0xaf64ada8,0xaa1f2da8,0x2f642da8,0x2a1fada8,0x2a1f3000,0x2f648000,0xaa1fb000,0xaf640000,
0xaea7263e,0x2c722fd9,0x2ea7a63e,0xac72afd9,0x2fd92c72,0x263eaea7,0xafd9ac72,0xa63e2ea7,0xac72afd9,0xaea7263e,0x2c722fd9,0x2ea7a63e,0xa63e2ea7,0x2fd92c72,0x263eaea7,0xafd9ac72,
0xada82da8,0xada82da8,0xada82da8,0xada82da8,0x2da8ada8,0x2da8ada8,0x2da8ada8,0x2da8ada8,0x2da82da8,0x2da82da8,0x2da82da8,0x2da82da8,0xada8ada8,0xada8ada8,0xada8ada8,0xada8ada8,
0x3000,0x3000,0x3000,0x80003000,0x8000b000,0x8000b000,0x8000b000,0x8000b000,0x30000000,0x30008000,0x30008000,0x30008000,0xb0000000,0xb0000000,0xb0000000,0xb0000000,
0x2ea7263e,0xac722fd9,0xaea7a63e,0x2c72afd9,0xafd92c72,0xa63eaea7,0x2fd9ac72,0x263e2ea7,0x2c72afd9,0x2ea7263e,0xac722fd9,0xaea7a63e,0x263e2ea7,0xafd92c72,0xa63eaea7,0x2fd9ac72,
0x2f64ada8,0x2a1f2da8,0xaf642da8,0xaa1fada8,0xaa1f3000,0xaf640000,0x2a1fb000,0x2f648000,0xaa1fada8,0x2f64ada8,0x2a1f2da8,0xaf642da8,0x2f640000,0xaa1f3000,0xaf640000,0x2a1fb000,
0xaa1f2f64,0x2a1faf64,0xaa1f2f64,0x2a1faf64,0x2f64aa1f,0xaf642a1f,0x2f64aa1f,0xaf642a1f,0xaf642a1f,0x2f64aa1f,0xaf642a1f,0x2f64aa1f,0xaa1f2f64,0x2a1faf64,0xaa1f2f64,0x2a1faf64,
0x2da80000,0xada80000,0x2da88000,0xada80000,0x2da8b000,0xada83000,0x2da8b000,0xada83000,0xada83000,0x2da8b000,0xada83000,0x2da8b000,0x2da88000,0xada80000,0x2da88000,0xada88000,
0xa63e2c72,0x2fd9aea7,0x263eac72,0xafd92ea7,0xaea72fd9,0x2c72a63e,0x2ea7afd9,0xac72263e,0xafd92ea7,0xa63e2c72,0x2fd9aea7,0x263eac72,0xac72263e,0xaea72fd9,0x2c72a63e,0x2ea7afd9,
0x2f64ada8,0x2a1fada8,0xaf642da8,0xaa1f2da8,0x2a1f0000,0x2f64b000,0xaa1f0000,0xaf643000,0xaa1f2da8,0x2f64ada8,0x2a1fada8,0xaf642da8,0xaf643000,0x2a1f8000,0x2f64b000,0xaa1f8000,
0xb0003000,0xb0003000,0xb0003000,0xb0003000,0xb0003000,0xb0003000,0xb0003000,0xb0003000,0x0,0x8000,0x8000,0x80008000,0x8000,0x8000,0x8000,0x8000,
0x80000000,0x80000000,0x80008000,0x80008000,0x80000000,0x80008000,0x80008000,0x80008000,0xb0003000,0xb0003000,0xb0003000,0xb0003000,0xb0003000,0xb0003000,0xb0003000,0xb0003000,
0xaa1f2da8,0x2f64ada8,0x2a1fada8,0xaf642da8,0xaf643000,0x2a1f0000,0x2f64b000,0xaa1f8000,0xaf642da8,0xaa1f2da8,0x2f64ada8,0x2a1fada8,0xaa1f0000,0xaf643000,0x2a1f0000,0x2f64b000,
0x2fd9aea7,0x263eac72,0xafd92ea7,0xa63e2c72,0x2c72a63e,0x2ea7afd9,0xac72263e,0xaea72fd9,0xa63e2c72,0x2fd9aea7,0x263eac72,0xafd92ea7,0xaea72fd9,0x2c72a63e,0x2ea7afd9,0xac72263e,
0xada80000,0x2da80000,0xada88000,0x2da80000,0xada83000,0x2da8b000,0xada83000,0x2da8b000,0xada83000,0x2da8b000,0xada83000,0x2da8b000,0x2da80000,0xada88000,0x2da88000,0xada88000,
0xaa1f2f64,0x2a1faf64,0xaa1f2f64,0x2a1faf64,0x2f64aa1f,0xaf642a1f,0x2f64aa1f,0xaf642a1f,0x2f64aa1f,0xaf642a1f,0x2f64aa1f,0xaf642a1f,0x2a1faf64,0xaa1f2f64,0x2a1faf64,0xaa1f2f64,
0x2a1f2da8,0xaf642da8,0xaa1fada8,0x2f64ada8,0xaf640000,0x2a1fb000,0x2f640000,0xaa1f3000,0x2f64ada8,0x2a1f2da8,0xaf642da8,0xaa1fada8,0xaa1f3000,0xaf648000,0x2a1fb000,0x2f640000,
0x2c72afd9,0x2ea7263e,0xac722fd9,0xaea7a63e,0x263e2ea7,0xafd92c72,0xa63eaea7,0x2fd9ac72,0xaea7a63e,0x2c72afd9,0x2ea7263e,0xac722fd9,0x2fd9ac72,0x263e2ea7,0xafd92c72,0xa63eaea7,
0x2da8ada8,0x2da8ada8,0x2da8ada8,0x2da8ada8,0xada82da8,0xada82da8,0xada82da8,0xada82da8,0x2da82da8,0x2da82da8,0x2da82da8,0x2da82da8,0xada8ada8,0xada8ada8,0xada8ada8,0xada8ada8,
0x80003000,0x80003000,0x80003000,0x3000,0xb000,0x8000b000,0xb000,0xb000,0xb0000000,0xb0008000,0xb0008000,0xb0008000,0x30000000,0x30000000,0x30000000,0x30008000,
0x2c722fd9,0x2ea7a63e,0xac72afd9,0xaea7263e,0x263eaea7,0xafd9ac72,0xa63e2ea7,0x2fd92c72,0xaea7263e,0x2c722fd9,0x2ea7a63e,0xac72afd9,0x2fd92c72,0x263eaea7,0xafd9ac72,0xa63e2ea7,
0xaf64ada8,0xaa1f2da8,0x2f642da8,0x2a1fada8,0x2a1f3000,0x2f648000,0xaa1fb000,0xaf648000,0x2a1fada8,0xaf64ada8,0xaa1f2da8,0x2f642da8,0xaf640000,0x2a1f3000,0x2f648000,0xaa1fb000,
0x2f642a1f,0xaf64aa1f,0x2f642a1f,0xaf64aa1f,0x2a1f2f64,0xaa1faf64,0x2a1f2f64,0xaa1faf64,0xaa1faf64,0x2a1f2f64,0xaa1faf64,0x2a1f2f64,0x2f642a1f,0xaf64aa1f,0x2f642a1f,0xaf64aa1f,
0xada80000,0x2da80000,0xada88000,0x2da88000,0xada8b000,0x2da83000,0xada8b000,0x2da83000,0x2da83000,0xada8b000,0x2da83000,0xada8b000,0xada88000,0x2da88000,0xada88000,0x2da80000,
0x2fd92ea7,0x263e2c72,0xafd9aea7,0xa63eac72,0x2c72263e,0x2ea72fd9,0xac72a63e,0xaea7afd9,0xa63eac72,0x2fd92ea7,0x263e2c72,0xafd9aea7,0xaea7afd9,0x2c72263e,0x2ea72fd9,0xac72a63e,
0xaf64ada8,0xaa1fada8,0x2f642da8,0x2a1f2da8,0xaa1f0000,0xaf64b000,0x2a1f0000,0x2f643000,0x2a1f2da8,0xaf64ada8,0xaa1fada8,0x2f642da8,0x2f643000,0xaa1f8000,0xaf64b000,0x2a1f0000,
0x80008000,0x80008000,0x80008000,0x80008000,0x80008000,0x80008000,0x80008000,0x80008000,0x30003000,0x30003000,0x30003000,0x30003000,0x30003000,0x30003000,0x30003000,0x30003000,
0x80008000,0x80008000,0x80008000,0x80008000,0x80008000,0x80008000,0x80008000,0x80008000,0x30003000,0x30003000,0x30003000,0x30003000,0x30003000,0x30003000,0x30003000,0x30003000,
0xaf64ada8,0xaa1fada8,0x2f642da8,0x2a1f2da8,0xaa1f8000,0xaf64b000,0x2a1f8000,0x2f643000,0x2a1f2da8,0xaf64ada8,0xaa1fada8,0x2f642da8,0x2f643000,0xaa1f0000,0xaf64b000,0x2a1f8000,
0xafd9aea7,0xa63eac72,0x2fd92ea7,0x263e2c72,0xac72a63e,0xaea7afd9,0x2c72263e,0x2ea72fd9,0x263e2c72,0xafd9aea7,0xa63eac72,0x2fd92ea7,0x2ea72fd9,0xac72a63e,0xaea7afd9,0x2c72263e,
0x2da83000,0xada8b000,0x2da83000,0xada8b000,0xada80000,0x2da88000,0xada80000,0x2da88000,0xada88000,0x2da88000,0xada80000,0x2da88000,0xada8b000,0x2da83000,0xada8b000,0x2da83000,
0x2a1f2f64,0xaa1faf64,0x2a1f2f64,0xaa1faf64,0xaf64aa1f,0x2f642a1f,0xaf64aa1f,0x2f642a1f,0xaf64aa1f,0x2f642a1f,0xaf64aa1f,0x2f642a1f,0xaa1faf64,0x2a1f2f64,0xaa1faf64,0x2a1f2f64,
0xaf64ada8,0xaa1f2da8,0x2f642da8,0x2a1fada8,0x2a1f3000,0x2f648000,0xaa1fb000,0xaf640000,0x2a1fada8,0xaf64ada8,0xaa1f2da8,0x2f642da8,0xaf648000,0x2a1f3000,0x2f648000,0xaa1fb000,
0xac72afd9,0xaea7263e,0x2c722fd9,0x2ea7a63e,0xa63e2ea7,0x2fd92c72,0x263eaea7,0xafd9ac72,0x2ea7a63e,0xac72afd9,0xaea7263e,0x2c722fd9,0xafd9ac72,0xa63e2ea7,0x2fd92c72,0x263eaea7,
0xada8ada8,0xada8ada8,0xada8ada8,0xada8ada8,0x2da82da8,0x2da82da8,0x2da82da8,0x2da82da8,0xada82da8,0xada82da8,0xada82da8,0xada82da8,0x2da8ada8,0x2da8ada8,0x2da8ada8,0x2da8ada8,
0xb0008000,0xb0000000,0xb0000000,0xb0000000,0x30008000,0x30008000,0x30008000,0x30008000,0x3000,0x3000,0x3000,0x80003000,0x8000b000,0x8000b000,0x8000b000,0x8000b000,
0xac722fd9,0xaea7a63e,0x2c72afd9,0x2ea7263e,0xa63eaea7,0x2fd9ac72,0x263e2ea7,0xafd92c72,0x2ea7263e,0xac722fd9,0xaea7a63e,0x2c72afd9,0xafd92c72,0xa63eaea7,0x2fd9ac72,0x263e2ea7,
0x2a1f2da8,0xaf642da8,0xaa1fada8,0x2f64ada8,0xaf648000,0x2a1fb000,0x2f648000,0xaa1f3000,0x2f64ada8,0x2a1f2da8,0xaf642da8,0xaa1fada8,0xaa1f3000,0xaf640000,0x2a1fb000,0x2f648000,
0xaf642a1f,0x2f64aa1f,0xaf642a1f,0x2f64aa1f,0xaa1f2f64,0x2a1faf64,0xaa1f2f64,0x2a1faf64,0x2a1faf64,0xaa1f2f64,0x2a1faf64,0xaa1f2f64,0xaf642a1f,0x2f64aa1f,0xaf642a1f,0x2f64aa1f,
0xada83000,0x2da8b000,0xada83000,0x2da8b000,0x2da88000,0xada80000,0x2da88000,0xada88000,0xada88000,0x2da88000,0xada80000,0x2da88000,0xada83000,0x2da8b000,0xada83000,0x2da8b000,
0xafd92ea7,0xa63e2c72,0x2fd9aea7,0x263eac72,0xac72263e,0xaea72fd9,0x2c72a63e,0x2ea7afd9,0x263eac72,0xafd92ea7,0xa63e2c72,0x2fd9aea7,0x2ea7afd9,0xac72263e,0xaea72fd9,0x2c72a63e,
0xaa1f2da8,0x2f64ada8,0x2a1fada8,0xaf642da8,0xaf643000,0x2a1f8000,0x2f64b000,0xaa1f8000,0xaf642da8,0xaa1f2da8,0x2f64ada8,0x2a1fada8,0xaa1f8000,0xaf643000,0x2a1f8000,0x2f64b000,
0x80008000,0x80000000,0x80000000,0x0,0x80000000,0x80000000,0x80000000,0x80000000,0xb0003000,0xb0003000,0xb0003000,0xb0003000,0xb0003000,0xb0003000,0xb0003000,0xb0003000,
0x3000b000,0x3000b000,0x3000b000,0x3000b000,0x3000b000,0x3000b000,0x3000b000,0x3000b000,0x80000000,0x80000000,0x80008000,0x80008000,0x80000000,0x80008000,0x80008000,0x80008000,
0x2f64ada8,0x2a1fada8,0xaf642da8,0xaa1f2da8,0x2a1f8000,0x2f64b000,0xaa1f8000,0xaf643000,0xaa1f2da8,0x2f64ada8,0x2a1fada8,0xaf642da8,0xaf643000,0x2a1f0000,0x2f64b000,0xaa1f8000,
0x263eac72,0xafd92ea7,0xa63e2c72,0x2fd9aea7,0x2ea7afd9,0xac72263e,0xaea72fd9,0x2c72a63e,0x2fd9aea7,0x263eac72,0xafd92ea7,0xa63e2c72,0x2c72a63e,0x2ea7afd9,0xac72263e,0xaea72fd9,
0xada83000,0x2da8b000,0xada83000,0x2da8b000,0x2da80000,0xada88000,0x2da88000,0xada88000,0x2da88000,0xada88000,0x2da80000,0xada88000,0x2da8b000,0xada83000,0x2da8b000,0xada83000,
0x2f64aa1f,0xaf642a1f,0x2f64aa1f,0xaf642a1f,0x2a1faf64,0xaa1f2f64,0x2a1faf64,0xaa1f2f64,0x2a1faf64,0xaa1f2f64,0x2a1faf64,0xaa1f2f64,0xaf642a1f,0x2f64aa1f,0xaf642a1f,0x2f64aa1f,
0x2f64ada8,0x2a1f2da8,0xaf642da8,0xaa1fada8,0xaa1f3000,0xaf648000,0x2a1fb000,0x2f640000,0xaa1fada8,0x2f64ada8,0x2a1f2da8,0xaf642da8,0x2f648000,0xaa1f3000,0xaf648000,0x2a1fb000,
0xaea7a63e,0x2c72afd9,0x2ea7263e,0xac722fd9,0x2fd9ac72,0x263e2ea7,0xafd92c72,0xa63eaea7,0xac722fd9,0xaea7a63e,0x2c72afd9,0x2ea7263e,0xa63eaea7,0x2fd9ac72,0x263e2ea7,0xafd92c72,
0xada8ada8,0xada8ada8,0xada8ada8,0xada8ada8,0x2da82da8,0x2da82da8,0x2da82da8,0x2da82da8,0x2da8ada8,0x2da8ada8,0x2da8ada8,0x2da8ada8,0xada82da8,0xada82da8,0xada82da8,0xada82da8,
0x30008000,0x30000000,0x30000000,0x30000000,0xb0008000,0xb0008000,0xb0008000,0xb0000000,0x80003000,0x80003000,0x80003000,0x3000,0xb000,0x8000b000,0xb000,0xb000,
0x2ea7a63e,0xac72afd9,0xaea7263e,0x2c722fd9,0xafd9ac72,0xa63e2ea7,0x2fd92c72,0x263eaea7,0x2c722fd9,0x2ea7a63e,0xac72afd9,0xaea7263e,0x263eaea7,0xafd9ac72,0xa63e2ea7,0x2fd92c72,
0xaa1f2da8,0x2f642da8,0x2a1fada8,0xaf64ada8,0x2f648000,0xaa1fb000,0xaf640000,0x2a1f3000,0xaf64ada8,0xaa1f2da8,0x2f642da8,0x2a1fada8,0x2a1f3000,0x2f648000,0xaa1fb000,0xaf648000,
0xaa1faf64,0x2a1f2f64,0xaa1faf64,0x2a1f2f64,0x2f642a1f,0xaf64aa1f,0x2f642a1f,0xaf64aa1f,0xaf64aa1f,0x2f642a1f,0xaf64aa1f,0x2f642a1f,0xaa1faf64,0x2a1f2f64,0xaa1faf64,0x2a1f2f64,
0x2da83000,0xada8b000,0x2da83000,0xada8b000,0xada88000,0x2da88000,0xada88000,0x2da80000,0x2da88000,0xada88000,0x2da80000,0xada80000,0x2da83000,0xada8b000,0x2da83000,0xada8b000,
0xa63eac72,0x2fd92ea7,0x263e2c72,0xafd9aea7,0xaea7afd9,0x2c72263e,0x2ea72fd9,0xac72a63e,0xafd9aea7,0xa63eac72,0x2fd92ea7,0x263e2c72,0xac72a63e,0xaea7afd9,0x2c72263e,0x2ea72fd9,
0x2a1f2da8,0xaf64ada8,0xaa1fada8,0x2f642da8,0x2f643000,0xaa1f8000,0xaf64b000,0x2a1f0000,0x2f642da8,0x2a1f2da8,0xaf64ada8,0xaa1fada8,0x2a1f8000,0x2f643000,0xaa1f8000,0xaf64b000,
0x3c003c00,0x3c003c00,0x3c003c00,0x3c003c00,0x3c003c00,0x3c003c00,0x3c003c00,0x3c003c00,0x80008000,0x80008000,0x80008000,0x80008000,0x80008000,0x80008000,0x80008000,0x80008000,
0x3bd93c00,0x3aa73b64,0x387239a8,0x323e361f,0xb23e0000,0xb872b61f,0xbaa7b9a8,0xbbd9bb64,0xb23e8000,0xb872b61f,0xbaa7b9a8,0xbbd9bb64,0xbbd9bc00,0xbaa7bb64,0xb872b9a8,0xb23eb61f,
0xbb64bc00,0xb61fb9a8,0x361f8000,0x3b6439a8,0x3b643c00,0x361f39a8,0xb61f0000,0xbb64b9a8,0x361f8000,0x3b6439a8,0x3b643c00,0x361f39a8,0xb61f8000,0xbb64b9a8,0xbb64bc00,0xb61fb9a8,
0x38728000,0x3bd93b64,0x323e39a8,0xbaa7b61f,0x3aa73c00,0xb23e361f,0xbbd9b9a8,0xb872bb64,0x3aa73c00,0xb23e361f,0xbbd9b9a8,0xb872bb64,0xb8728000,0xbbd9bb64,0xb23eb9a8,0x3aa7361f,
0xbc008000,0x3c008000,0xbc000000,0x3c008000,0xbc000000,0x3c008000,0xbc000000,0x3c008000,0x3c00,0x8000bc00,0x3c00,0x8000bc00,0x3c00,0x8000bc00,0x80003c00,0x8000bc00,
0xbbd98000,0x3aa7361f,0xb872b9a8,0x323e3b64,0x323ebc00,0xb8723b64,0x3aa7b9a8,0xbbd9361f,0xb23e3c00,0x3872bb64,0xbaa739a8,0x3bd9b61f,0xbbd90000,0x3aa7361f,0xb872b9a8,0x323e3b64,
0x3b648000,0xb61fb9a8,0xb61f3c00,0x3b64b9a8,0xbb648000,0x361f39a8,0x361fbc00,0xbb6439a8,0x361fbc00,0xbb6439a8,0x3b648000,0xb61fb9a8,0xb61f3c00,0x3b64b9a8,0xbb640000,0x361f39a8,
0xb8723c00,0x3bd9b61f,0xb23eb9a8,0xbaa73b64,0xbaa78000,0xb23e3b64,0x3bd9b9a8,0xb872b61f,0x3aa78000,0x323ebb64,0xbbd939a8,0x3872361f,0xb8723c00,0x3bd9b61f,0xb23eb9a8,0xbaa73b64,
0xbbd93c00,0xbaa73b64,0xb87239a8,0xb23e361f,0x323e8000,0x3872b61f,0x3aa7b9a8,0x3bd9bb64,0x323e8000,0x3872b61f,0x3aa7b9a8,0x3bd9bb64,0x3bd9bc00,0x3aa7bb64,0x3872b9a8,0x323eb61f,
0xbc003c00,0xbc003c00,0xbc003c00,0xbc003c00,0xbc003c00,0xbc003c00,0xbc003c00,0xbc003c00,0x80008000,0x80000000,0x80000000,0x80000000,0x80000000,0x80000000,0x0,0x80000000,
0xb8728000,0xbbd93b64,0xb23e39a8,0x3aa7b61f,0xbaa73c00,0x323e361f,0x3bd9b9a8,0x3872bb64,0xbaa73c00,0x323e361f,0x3bd9b9a8,0x3872bb64,0x38728000,0x3bd9bb64,0x323eb9a8,0xbaa7361f,
0x3b64bc00,0x361fb9a8,0xb61f8000,0xbb6439a8,0xbb643c00,0xb61f39a8,0x361f0000,0x3b64b9a8,0xb61f8000,0xbb6439a8,0xbb643c00,0xb61f39a8,0x361f8000,0x3b64b9a8,0x3b64bc00,0x361fb9a8,
0x3bd98000,0xbaa7361f,0x3872b9a8,0xb23e3b64,0xb23ebc00,0x38723b64,0xbaa7b9a8,0x3bd9361f,0x323e3c00,0xb872bb64,0x3aa739a8,0xbbd9b61f,0x3bd98000,0xbaa7361f,0x3872b9a8,0xb23e3b64,
0x3c008000,0xbc008000,0x3c000000,0xbc008000,0x3c000000,0xbc008000,0x3c000000,0xbc000000,0x80003c00,0xbc00,0x80003c00,0x8000bc00,0x80003c00,0xbc00,0x80003c00,0xbc00,
0x38723c00,0xbbd9b61f,0x323eb9a8,0x3aa73b64,0x3aa78000,0x323e3b64,0xbbd9b9a8,0x3872b61f,0xbaa78000,0xb23ebb64,0x3bd939a8,0xb872361f,0x38723c00,0xbbd9b61f,0x323eb9a8,0x3aa73b64,
0xbb640000,0x361fb9a8,0x361f3c00,0xbb64b9a8,0x3b648000,0xb61f39a8,0xb61fbc00,0x3b6439a8,0xb61fbc00,0x3b6439a8,0xbb640000,0x361fb9a8,0x361f3c00,0xbb64b9a8,0x3b648000,0xb61f39a8,
0x39a83c00,0xb9a80000,0xb9a8bc00,0x39a88000,0x39a83c00,0xb9a80000,0xb9a8bc00,0x39a88000,0xb9a88000,0xb9a8bc00,0x39a88000,0x39a83c00,0xb9a80000,0xb9a8bc00,0x39a88000,0x39a83c00,
0x38723c00,0xbbd9b61f,0x323eb9a8,0x3aa73b64,0xbaa70000,0xb23ebb64,0x3bd939a8,0xb872361f,0xbaa78000,0xb23ebb64,0x3bd939a8,0xb872361f,0xb872bc00,0x3bd9361f,0xb23e39a8,0xbaa7bb64,
0xb61fbc00,0x3b6439a8,0xbb640000,0x361fb9a8,0x361f3c00,0xbb64b9a8,0x3b648000,0xb61f39a8,0x3b648000,0xb61f39a8,0xb61fbc00,0x3b6439a8,0xbb648000,0x361fb9a8,0x361f3c00,0xbb64b9a8,
0x3bd98000,0xbaa7361f,0x3872b9a8,0xb23e3b64,0x323e3c00,0xb872bb64,0x3aa739a8,0xbbd9b61f,0x323e3c00,0xb872bb64,0x3aa739a8,0xbbd9b61f,0xbbd98000,0x3aa7b61f,0xb87239a8,0x323ebb64,
0xb9a88000,0xb9a83c00,0x39a88000,0x39a8bc00,0xb9a80000,0xb9a83c00,0x39a88000,0x39a8bc00,0xb9a83c00,0x39a88000,0x39a8bc00,0xb9a80000,0xb9a83c00,0x39a88000,0x39a8bc00,0xb9a88000,
0xb8728000,0xbbd93b64,0xb23e39a8,0x3aa7b61f,0x3aa7bc00,0xb23eb61f,0xbbd939a8,0xb8723b64,0xbaa73c00,0x323e361f,0x3bd9b9a8,0x3872bb64,0xb8728000,0xbbd93b64,0xb23e39a8,0x3aa7b61f,
0x361f8000,0x3b64b9a8,0x3b64bc00,0x361fb9a8,0xb61f8000,0xbb6439a8,0xbb643c00,0xb61f39a8,0x3b64bc00,0x361fb9a8,0xb61f8000,0xbb6439a8,0xbb643c00,0xb61f39a8,0x361f8000,0x3b64b9a8,
0xbbd93c00,0xbaa73b64,0xb87239a8,0xb23e361f,0xb23e8000,0xb872361f,0xbaa739a8,0xbbd93b64,0x323e8000,0x3872b61f,0x3aa7b9a8,0x3bd9bb64,0xbbd93c00,0xbaa73b64,0xb87239a8,0xb23e361f,
0xb8723c00,0x3bd9b61f,0xb23eb9a8,0xbaa73b64,0x3aa78000,0x323ebb64,0xbbd939a8,0x3872361f,0x3aa78000,0x323ebb64,0xbbd939a8,0x3872361f,0x3872bc00,0xbbd9361f,0x323e39a8,0x3aa7bb64,
0xb9a83c00,0x39a80000,0x39a8bc00,0xb9a88000,0xb9a83c00,0x39a88000,0x39a8bc00,0xb9a88000,0x39a88000,0x39a8bc00,0xb9a88000,0xb9a83c00,0x39a80000,0x39a8bc00,0xb9a88000,0xb9a83c00,
0xbbd98000,0x3aa7361f,0xb872b9a8,0x323e3b64,0xb23e3c00,0x3872bb64,0xbaa739a8,0x3bd9b61f,0xb23e3c00,0x3872bb64,0xbaa739a8,0x3bd9b61f,0x3bd98000,0xbaa7b61f,0x387239a8,0xb23ebb64,
0x361fbc00,0xbb6439a8,0x3b640000,0xb61fb9a8,0xb61f3c00,0x3b64b9a8,0xbb648000,0x361f39a8,0xbb648000,0x361f39a8,0x361fbc00,0xbb6439a8,0x3b648000,0xb61fb9a8,0xb61f3c00,0x3b64b9a8,
0x38728000,0x3bd93b64,0x323e39a8,0xbaa7b61f,0xbaa7bc00,0x323eb61f,0x3bd939a8,0x38723b64,0x3aa73c00,0xb23e361f,0xbbd9b9a8,0xb872bb64,0x38728000,0x3bd93b64,0x323e39a8,0xbaa7b61f,
0x39a88000,0x39a83c00,0xb9a88000,0xb9a8bc00,0x39a80000,0x39a83c00,0xb9a80000,0xb9a8bc00,0x39a83c00,0xb9a88000,0xb9a8bc00,0x39a88000,0x39a83c00,0xb9a88000,0xb9a8bc00,0x39a80000,
0x3bd93c00,0x3aa73b64,0x387239a8,0x323e361f,0x323e8000,0x3872361f,0x3aa739a8,0x3bd93b64,0xb23e8000,0xb872b61f,0xbaa7b9a8,0xbbd9bb64,0x3bd93c00,0x3aa73b64,0x387239a8,0x323e361f,
0xb61f8000,0xbb64b9a8,0xbb64bc00,0xb61fb9a8,0x361f8000,0x3b6439a8,0x3b643c00,0x361f39a8,0xbb64bc00,0xb61fb9a8,0x361f0000,0x3b6439a8,0x3b643c00,0x361f39a8,0xb61f8000,0xbb64b9a8,
0x0,0x0,0x0,0x0,0x0,0x0,0x0,0x0,0x3c003c00,0x3c003c00,0x3c003c00,0x3c003c00,0x3c003c00,0x3c003c00,0x3c003c00,0x3c003c00,
0x323e0000,0x3872361f,0x3aa739a8,0x3bd93b64,0x3bd93c00,0x3aa73b64,0x387239a8,0x323e361f,0x3bd93c00,0x3aa73b64,0x387239a8,0x323e361f,0xb23e0000,0xb872b61f,0xbaa7b9a8,0xbbd9bb64,
0xb61f0000,0xbb64b9a8,0xbb64bc00,0xb61fb9a8,0x361f0000,0x3b6439a8,0x3b643c00,0x361f39a8,0xbb64bc00,0xb61fb9a8,0x361f8000,0x3b6439a8,0x3b643c00,0x361f39a8,0xb61f0000,0xbb64b9a8,
0xbaa7bc00,0x323eb61f,0x3bd939a8,0x38723b64,0x38720000,0x3bd93b64,0x323e39a8,0xbaa7b61f,0x38728000,0x3bd93b64,0x323e39a8,0xbaa7b61f,0x3aa73c00,0xb23e361f,0xbbd9b9a8,0xb872bb64,
0x3c00,0x8000bc00,0x3c00,0x8000bc00,0x3c00,0x8000bc00,0x80003c00,0x8000bc00,0x3c000000,0xbc000000,0x3c008000,0xbc000000,0x3c008000,0xbc000000,0x3c008000,0xbc000000,
0xb23e3c00,0x3872bb64,0xbaa739a8,0x3bd9b61f,0xbbd90000,0x3aa7361f,0xb872b9a8,0x323e3b64,0x3bd90000,0xbaa7b61f,0x387239a8,0xb23ebb64,0xb23e3c00,0x3872bb64,0xbaa739a8,0x3bd9b61f,
0x361fbc00,0xbb6439a8,0x3b648000,0xb61fb9a8,0xb61f3c00,0x3b64b9a8,0xbb640000,0x361f39a8,0xbb640000,0x361f39a8,0x361fbc00,0xbb6439a8,0x3b640000,0xb61fb9a8,0xb61f3c00,0x3b64b9a8,
0x3aa78000,0x323ebb64,0xbbd939a8,0x3872361f,0xb8723c00,0x3bd9b61f,0xb23eb9a8,0xbaa73b64,0x3872bc00,0xbbd9361f,0x323e39a8,0x3aa7bb64,0x3aa70000,0x323ebb64,0xbbd939a8,0x3872361f,
0xb23e0000,0xb872361f,0xbaa739a8,0xbbd93b64,0xbbd93c00,0xbaa73b64,0xb87239a8,0xb23e361f,0xbbd93c00,0xbaa73b64,0xb87239a8,0xb23e361f,0x323e8000,0x3872b61f,0x3aa7b9a8,0x3bd9bb64,
0x0,0x8000,0x8000,0x8000,0x8000,0x8000,0x80008000,0x8000,0xbc003c00,0xbc003c00,0xbc003c00,0xbc003c00,0xbc003c00,0xbc003c00,0xbc003c00,0xbc003c00,
0x3aa7bc00,0xb23eb61f,0xbbd939a8,0xb8723b64,0xb8720000,0xbbd93b64,0xb23e39a8,0x3aa7b61f,0xb8728000,0xbbd93b64,0xb23e39a8,0x3aa7b61f,0xbaa73c00,0x323e361f,0x3bd9b9a8,0x3872bb64,
0x361f0000,0x3b64b9a8,0x3b64bc00,0x361fb9a8,0xb61f0000,0xbb6439a8,0xbb643c00,0xb61f39a8,0x3b64bc00,0x361fb9a8,0xb61f8000,0xbb6439a8,0xbb643c00,0xb61f39a8,0x361f0000,0x3b64b9a8,
0x323e3c00,0xb872bb64,0x3aa739a8,0xbbd9b61f,0x3bd98000,0xbaa7361f,0x3872b9a8,0xb23e3b64,0xbbd90000,0x3aa7b61f,0xb87239a8,0x323ebb64,0x323e3c00,0xb872bb64,0x3aa739a8,0xbbd9b61f,
0x80003c00,0xbc00,0x80003c00,0x8000bc00,0x80003c00,0xbc00,0x80003c00,0xbc00,0xbc000000,0x3c000000,0xbc008000,0x3c000000,0xbc008000,0x3c000000,0xbc008000,0x3c008000,
0xbaa78000,0xb23ebb64,0x3bd939a8,0xb872361f,0x38723c00,0xbbd9b61f,0x323eb9a8,0x3aa73b64,0xb872bc00,0x3bd9361f,0xb23e39a8,0xbaa7bb64,0xbaa70000,0xb23ebb64,0x3bd939a8,0xb872361f,
0xb61fbc00,0x3b6439a8,0xbb640000,0x361fb9a8,0x361f3c00,0xbb64b9a8,0x3b648000,0xb61f39a8,0x3b648000,0xb61f39a8,0xb61fbc00,0x3b6439a8,0xbb640000,0x361fb9a8,0x361f3c00,0xbb64b9a8,
0x39a80000,0x39a83c00,0xb9a80000,0xb9a8bc00,0x39a88000,0x39a83c00,0xb9a80000,0xb9a8bc00,0x39a83c00,0xb9a80000,0xb9a8bc00,0x39a88000,0x39a83c00,0xb9a80000,0xb9a8bc00,0x39a88000,
0x3aa70000,0x323e3b64,0xbbd9b9a8,0x3872b61f,0x38723c00,0xbbd9b61f,0x323eb9a8,0x3aa73b64,0x38723c00,0xbbd9b61f,0x323eb9a8,0x3aa73b64,0xbaa70000,0xb23ebb64,0x3bd939a8,0xb872361f,
0xbb640000,0x361fb9a8,0x361f3c00,0xbb64b9a8,0x3b640000,0xb61f39a8,0xb61fbc00,0x3b6439a8,0xb61fbc00,0x3b6439a8,0xbb640000,0x361fb9a8,0x361f3c00,0xbb64b9a8,0x3b648000,0xb61f39a8,
0xb23ebc00,0x38723b64,0xbaa7b9a8,0x3bd9361f,0x3bd90000,0xbaa7361f,0x3872b9a8,0xb23e3b64,0x3bd98000,0xbaa7361f,0x3872b9a8,0xb23e3b64,0x323e3c00,0xb872bb64,0x3aa739a8,0xbbd9b61f,
0xb9a83c00,0x39a88000,0x39a8bc00,0xb9a80000,0xb9a83c00,0x39a88000,0x39a8bc00,0xb9a88000,0x39a80000,0x39a8bc00,0xb9a80000,0xb9a83c00,0x39a88000,0x39a8bc00,0xb9a80000,0xb9a83c00,
0xbaa73c00,0x323e361f,0x3bd9b9a8,0x3872bb64,0xb8728000,0xbbd93b64,0xb23e39a8,0x3aa7b61f,0x38720000,0x3bd9bb64,0x323eb9a8,0xbaa7361f,0xbaa73c00,0x323e361f,0x3bd9b9a8,0x3872bb64,
0x3b64bc00,0x361fb9a8,0xb61f8000,0xbb6439a8,0xbb643c00,0xb61f39a8,0x361f8000,0x3b64b9a8,0xb61f0000,0xbb6439a8,0xbb643c00,0xb61f39a8,0x361f0000,0x3b64b9a8,0x3b64bc00,0x361fb9a8,
0x323e8000,0x3872b61f,0x3aa7b9a8,0x3bd9bb64,0xbbd93c00,0xbaa73b64,0xb87239a8,0xb23e361f,0x3bd9bc00,0x3aa7bb64,0x3872b9a8,0x323eb61f,0x323e0000,0x3872b61f,0x3aa7b9a8,0x3bd9bb64,
0xbaa70000,0xb23e3b64,0x3bd9b9a8,0xb872b61f,0xb8723c00,0x3bd9b61f,0xb23eb9a8,0xbaa73b64,0xb8723c00,0x3bd9b61f,0xb23eb9a8,0xbaa73b64,0x3aa78000,0x323ebb64,0xbbd939a8,0x3872361f,
0xb9a80000,0xb9a83c00,0x39a80000,0x39a8bc00,0xb9a88000,0xb9a83c00,0x39a80000,0x39a8bc00,0xb9a83c00,0x39a80000,0x39a8bc00,0xb9a88000,0xb9a83c00,0x39a88000,0x39a8bc00,0xb9a88000,
0x323ebc00,0xb8723b64,0x3aa7b9a8,0xbbd9361f,0xbbd90000,0x3aa7361f,0xb872b9a8,0x323e3b64,0xbbd98000,0x3aa7361f,0xb872b9a8,0x323e3b64,0xb23e3c00,0x3872bb64,0xbaa739a8,0x3bd9b61f,
0x3b640000,0xb61fb9a8,0xb61f3c00,0x3b64b9a8,0xbb640000,0x361f39a8,0x361fbc00,0xbb6439a8,0x361fbc00,0xbb6439a8,0x3b640000,0xb61fb9a8,0xb61f3c00,0x3b64b9a8,0xbb648000,0x361f39a8,
0x3aa73c00,0xb23e361f,0xbbd9b9a8,0xb872bb64,0x38728000,0x3bd93b64,0x323e39a8,0xbaa7b61f,0xb8720000,0xbbd9bb64,0xb23eb9a8,0x3aa7361f,0x3aa73c00,0xb23e361f,0xbbd9b9a8,0xb872bb64,
0x39a83c00,0xb9a88000,0xb9a8bc00,0x39a88000,0x39a83c00,0xb9a88000,0xb9a8bc00,0x39a80000,0xb9a80000,0xb9a8bc00,0x39a80000,0x39a83c00,0xb9a88000,0xb9a8bc00,0x39a88000,0x39a83c00,
0xb23e8000,0xb872b61f,0xbaa7b9a8,0xbbd9bb64,0x3bd93c00,0x3aa73b64,0x387239a8,0x323e361f,0xbbd9bc00,0xbaa7bb64,0xb872b9a8,0xb23eb61f,0xb23e0000,0xb872b61f,0xbaa7b9a8,0xbbd9bb64,
0xbb64bc00,0xb61fb9a8,0x361f0000,0x3b6439a8,0x3b643c00,0x361f39a8,0xb61f8000,0xbb64b9a8,0x361f0000,0x3b6439a8,0x3b643c00,0x361f39a8,0xb61f0000,0xbb64b9a8,0xbb64bc00,0xb61fb9a8,
};
__device__ __align__(1024) bf16 g_x1T[DM * XP];
__device__ __align__(1024) bf16 g_x2T[DM * XP];
__device__ __align__(1024) uint4 g_of[8][16][1280];
__device__ __align__(1024) float g_fs[2][SEQ];

#define TS_SMEM 0
#define TS_DECL
#define TS_ARG
#define TS_PASS
#define TS_PHASE(p)
#define TS(i)
#define TSX(row, i)
#define TS_BEGIN
#define TS_END

struct cplx { float r, i; };
__device__ __forceinline__ cplx cmul(cplx a, cplx b) {
    cplx o;
    o.r = fmaf(a.r, b.r, -a.i * b.i);
    o.i = fmaf(a.r, b.i, a.i * b.r);
    return o;
}
__device__ __forceinline__ cplx csq(cplx a) {
    cplx o;
    o.r = fmaf(a.r, a.r, -a.i * a.i);
    o.i = 2.f * a.r * a.i;
    return o;
}
__device__ __forceinline__ cplx cexp_p(float arl, float ai, float p) {
    float mag = ex2(arl * p);
    float ang = ai * p;
    float n = rintf(ang * 0.15915494309189535f);
    float r = fmaf(n, -6.2831854820251465f, ang);
    r = fmaf(n, 1.7484555e-7f, r);
    cplx o;
    o.r = mag * __cosf(r);
    o.i = mag * __sinf(r);
    return o;
}

__device__ __forceinline__ uint32_t pack2h(float lo, float hi) {
    uint32_t r;
    asm("cvt.rn.f16x2.f32 %0, %1, %2;" : "=r"(r) : "f"(hi), "f"(lo));
    return r;
}
__device__ __forceinline__ uint32_t hmul(uint32_t a, uint32_t b) { uint32_t d; asm("mul.rn.f16x2 %0, %1, %2;" : "=r"(d) : "r"(a), "r"(b)); return d; }
__device__ __forceinline__ uint32_t hfma(uint32_t a, uint32_t b, uint32_t c) { uint32_t d; asm("fma.rn.f16x2 %0, %1, %2, %3;" : "=r"(d) : "r"(a), "r"(b), "r"(c)); return d; }
__device__ __forceinline__ uint32_t hfms(uint32_t a, uint32_t b, uint32_t c) {
    uint32_t d;
    asm("{\n.reg .b32 n;\nneg.f16x2 n, %1;\nfma.rn.f16x2 %0, n, %2, %3;\n}" : "=r"(d) : "r"(a), "r"(b), "r"(c));
    return d;
}
__device__ __forceinline__ uint32_t hadd(uint32_t a, uint32_t b) { uint32_t d; asm("add.rn.f16x2 %0, %1, %2;" : "=r"(d) : "r"(a), "r"(b)); return d; }
__device__ __forceinline__ uint32_t hsub(uint32_t a, uint32_t b) { uint32_t d; asm("sub.rn.f16x2 %0, %1, %2;" : "=r"(d) : "r"(a), "r"(b)); return d; }
__device__ __forceinline__ uint4 ldg_tab(int tab, int t) { return ldg128((const uint4*)c_fft + t + tab * 128); }
__device__ __forceinline__ uint32_t u4(const uint4& v, int i) { return i == 0 ? v.x : i == 1 ? v.y : i == 2 ? v.z : v.w; }
struct cpair { uint32_t r, i; };
__device__ __forceinline__ cpair pmul(cpair p, uint32_t z) {
    const __half2 zv = *reinterpret_cast<const __half2*>(&z), pr = *reinterpret_cast<const __half2*>(&p.r), pi = *reinterpret_cast<const __half2*>(&p.i);
    const __half2 zr = __low2half2(zv), zi = __high2half2(zv);
    const __half2 a = __hfma2(__hneg2(pi), zi, __hmul2(pr, zr)), b = __hfma2(pi, zr, __hmul2(pr, zi));
    return {*reinterpret_cast<const uint32_t*>(&a), *reinterpret_cast<const uint32_t*>(&b)};
}
__device__ __forceinline__ uint32_t packz(cplx z) { return pack2h(z.r, z.i); }
__device__ __forceinline__ void wgmma_kg(float (&d)[24], uint64_t da, uint64_t db, int scale_d) {
    asm volatile("{\n.reg .pred p;\nsetp.ne.b32 p, %26, 0;\n"
                 "wgmma.mma_async.sync.aligned.m64n48k16.f32.f16.f16 "
                 "{%0,%1,%2,%3,%4,%5,%6,%7,%8,%9,%10,%11,%12,%13,%14,%15,%16,%17,%18,%19,%20,%21,%22,%23}, %24, %25, p, 1, 1, 1, 1;\n}\n"
                 : "+f"(d[0]), "+f"(d[1]), "+f"(d[2]), "+f"(d[3]), "+f"(d[4]), "+f"(d[5]), "+f"(d[6]), "+f"(d[7]), "+f"(d[8]), "+f"(d[9]),
                   "+f"(d[10]), "+f"(d[11]), "+f"(d[12]), "+f"(d[13]), "+f"(d[14]), "+f"(d[15]), "+f"(d[16]), "+f"(d[17]), "+f"(d[18]), "+f"(d[19]),
                   "+f"(d[20]), "+f"(d[21]), "+f"(d[22]), "+f"(d[23])
                 : "l"(da), "l"(db), "r"(scale_d));
}

struct SsmParams { const bf16 *lar, *aim, *cre, *cim, *logdt, *dskip; const unsigned* epoch; };
constexpr int KG_TABLES = 6 * 16384, KG_RES = 1664;
struct KgShared { uint32_t kmax[6], kexp[6]; float cinv[6], tap0[6]; };
struct KgParams { uint32_t l[3], a[3], r[3], i[3], dt, ds; };

__device__ __forceinline__ bool kg_is_hi(int warp) { return ((warp >> 1) ^ (warp >> 2)) & 1; }
__device__ __forceinline__ void kgen_load(KgParams& kp, int d0, int warp, int lane, const SsmParams& sp) {
    const int d = d0 + min(2 * (warp >> 2) + (warp & 1), 4), idx = d * (NMODE / 2) + lane;
    const bf16 *pr = kg_is_hi(warp) ? sp.cre : sp.lar, *pi = kg_is_hi(warp) ? sp.cim : sp.aim;
    kp.dt = __ldg((const uint16_t*)sp.logdt + d);
#pragma unroll
    for (int j = 0; j < 3; j++) {
        kp.l[j] = __ldg((const uint32_t*)sp.lar + idx + 32 * j); kp.a[j] = __ldg((const uint32_t*)sp.aim + idx + 32 * j);
        kp.r[j] = __ldg((const uint32_t*)pr + idx + 32 * j); kp.i[j] = __ldg((const uint32_t*)pi + idx + 32 * j);
    }
    kp.ds = __ldg((const uint16_t*)sp.dskip + d0 + min(warp >> 1, 4));
}

struct KgAnchors { uint32_t v[8]; };
__device__ __forceinline__ KgAnchors kg_anchor_lo(const KgParams& kp, uint32_t sel, float dt) {
    auto B = [&](uint32_t v) { return __uint_as_float(__byte_perm(v, 0u, sel)); };
    const float arl = -rbf(ex2(B(kp.l[0]) * 1.4426950408889634f)) * dt * 1.4426950408889634f, ai = B(kp.a[0]) * dt;
    const cplx z8 = cexp_p(arl, ai, 8.f), z16 = csq(z8), z24 = cmul(z16, z8), z32 = csq(z16), z64 = csq(z32), z128 = csq(z64), z192 = cmul(z128, z64);
    return {{pack2h(1.f, z8.r), pack2h(0.f, z8.i), pack2h(z16.r, z24.r), pack2h(z16.i, z24.i), packz(z32), packz(z64), packz(z128), packz(z192)}};
}
__device__ __forceinline__ KgAnchors kg_anchor_hi(const KgParams& kp, uint32_t sel, float dt, float cs) {
    auto B = [&](uint32_t v) { return __uint_as_float(__byte_perm(v, 0u, sel)); };
    const float arl = -rbf(ex2(B(kp.l[0]) * 1.4426950408889634f)) * dt * 1.4426950408889634f, ai = B(kp.a[0]) * dt;
    const cplx z1 = cexp_p(arl, -ai, 1.f), z2 = csq(z1), z4 = csq(z2), z256 = cexp_p(arl, -ai, 256.f), z512 = csq(z256), z1024 = csq(z512);
    const cplx H0 = {B(kp.r[0]) * cs, -B(kp.i[0]) * cs}, H4 = cmul(H0, z4);
    return {{pack2h(H0.r, H4.r), pack2h(H0.i, H4.i), packz(z1), packz(z2), packz(z256), packz(z512), packz(z1024), 0u}};
}

template <class Idle>
__device__ __forceinline__ void kgen_tables(KgParams& kp, uint32_t scr, uint32_t dump, KgShared* ks, int warp, int lane, Idle idle TS_ARG) {
    const int wg = warp >> 2, half = warp & 1, sw = lane & 7;
    const bool hi = kg_is_hi(warp);
    TS(23);
    const float dt = rbf(ex2(bf_lo(kp.dt) * 1.4426950408889634f));
    uint32_t sel = (wg == 2 && half) ? 0x3244u : 0x1044u;
    float cs = 0.f;
    KgAnchors an;
    if (hi) {
        uint32_t m = 0;
#pragma unroll
        for (int j = 0; j < 3; j++) m = __vmaxu2(m, __vmaxu2(kp.r[j] & 0x7FFF7FFFu, kp.i[j] & 0x7FFF7FFFu));
        m = __reduce_max_sync(~0u, max(m << 16, m & 0xFFFF0000u));
        const uint32_t e = min(max(__float_as_uint(2.f * dt * __uint_as_float(m)) >> 23, 2u), 252u);
        cs = 2.f * dt * __uint_as_float((253u - e) << 23);
        if (lane == 0) { ks->cinv[2 * wg + half] = __uint_as_float((e + 1u) << 23); ks->kmax[2 * wg + half] = 0u; }
        an = kg_anchor_hi(kp, sel, dt, cs);
    } else {
        an = kg_anchor_lo(kp, sel, dt);
    }
    float acc[24];
#pragma unroll
    for (int i = 0; i < 24; i++) acc[i] = 0.f;
    uint32_t tb = scr + 2 * wg * 16384 + lane * 128;
    uint64_t da = mkdesc(scr + 2 * wg * 16384, 4096, 1024, 1);
    int flip = 16384;
#pragma unroll 1
    for (int c = wg == 2 ? 1 : 0, step = wg == 2 ? 2 : 1; c < 6; c += step) {
        if (wg < 2) sel ^= 0x2200u;
        if (!hi) {
            if (c & 1) { kp.l[0] = kp.l[1]; kp.l[1] = kp.l[2]; kp.a[0] = kp.a[1]; kp.a[1] = kp.a[2]; }
            cpair p[4];
            p[0] = {an.v[0], an.v[1]}; p[1] = {an.v[2], an.v[3]};
            p[2] = pmul(p[0], an.v[4]); p[3] = pmul(p[1], an.v[4]);
#pragma unroll
            for (int j = 0; j < 4; j++) {
                cpair v[4];
#pragma unroll
                for (int i = 0; i < 4; i++) v[i] = j ? pmul(p[i], an.v[4 + j]) : p[i];
                const uint32_t a = tb + (((4 * half + j) ^ sw) << 4);
                sts128(a, make_uint4(v[0].r, v[1].r, v[2].r, v[3].r));
                sts128(a + 4096, make_uint4(v[0].i, v[1].i, v[2].i, v[3].i));
            }
            an = kg_anchor_lo(kp, sel, dt);
        } else {
            if (c & 1) {
#pragma unroll
                for (int j = 0; j < 2; j++) { kp.l[j] = kp.l[j + 1]; kp.a[j] = kp.a[j + 1]; kp.r[j] = kp.r[j + 1]; kp.i[j] = kp.i[j + 1]; }
            }
            const uint32_t h1 = an.v[2], h2 = an.v[3], h256 = an.v[4], h512 = an.v[5], h1024 = an.v[6];
            cpair p[11];
            p[0] = {an.v[0], an.v[1]};
            p[1] = pmul(p[0], h2); p[2] = pmul(p[0], h1); p[3] = pmul(p[1], h1);
            p[4] = pmul(p[0], h256); p[5] = pmul(p[1], h256); p[6] = pmul(p[0], h512); p[7] = pmul(p[4], h512);
            p[8] = pmul({__byte_perm(p[0].r, p[4].r, 0x5410), __byte_perm(p[0].i, p[4].i, 0x5410)}, h1024);
            p[9] = pmul(p[8], h512); p[10] = pmul(p[8], h1024);
#pragma unroll
            for (int j = 0; j < 3; j++) {
                const uint32_t a = tb + 8192 + (((3 * half + j) ^ sw) << 4);
                sts128(a, make_uint4(p[4 * j].r, p[4 * j + 1].r, p[4 * j + 2].r, p[j < 2 ? 4 * j + 3 : 10].r));
                sts128(a + 4096, make_uint4(p[4 * j].i, p[4 * j + 1].i, p[4 * j + 2].i, p[j < 2 ? 4 * j + 3 : 10].i));
            }
            an = kg_anchor_hi(kp, sel, dt, cs);
        }
        if (c == 0) TS(24);
        if (c == 3) TS(25);
        fence_async_smem();
        wg_wait<0>();
        named_bar(5 + wg, 128);
        wg_fence();
#pragma unroll
        for (int k = 0; k < 4; k++) wgmma_kg(acc, da + k * 128, da + 512 + k * 128, 1);
        wg_commit();
        tb += flip; da += flip >> 4; flip = -flip;
    }
    const bool up = warp & 2;
    const int r = 2 * wg + up, lo0 = 16 * half + (lane >> 2);
    const uint32_t o = dump + r * KG_RES + lo0 * 52 + 4 * (lane & 3);
    const float ci = __uint_as_float(lds32(s2u(&ks->cinv[r])));
    const float ds = warp <= 8 ? bf_lo(kp.ds) : 0.f;
    TS(26);
    idle();
    wg_wait<0>();
    float v[12], m = 0.f;
#pragma unroll
    for (int j = 0; j < 12; j++) { v[j] = up ? acc[12 + j] : acc[j]; m = fmaxf(m, fabsf(v[j])); }
#pragma unroll
    for (int j = 0; j < 6; j++) sts32(o + (j & 1) * 416 + (j >> 1) * 16, pack2h(v[2 * j], v[2 * j + 1]));
    const uint32_t mm = __reduce_max_sync(~0u, __float_as_uint(m));
    if (lane == 0) {
        asm volatile("red.shared.max.u32 [%0], %1;" ::"r"(s2u(&ks->kmax[r])), "r"(mm) : "memory");
        if (!half) ks->tap0[r] = fmaf(ci, v[0], ds);
    }
}
#define F_PPOS 0
#define F_STAG 4
__device__ __forceinline__ void wgmma_h64_rs(uint32_t (&d)[16], const uint4& a, uint64_t db, int scale_d) {
    asm volatile("{\n.reg .pred p;\nsetp.ne.b32 p, %21, 0;\n"
                 "wgmma.mma_async.sync.aligned.m64n64k16.f16.f16.f16 {%0,%1,%2,%3,%4,%5,%6,%7,%8,%9,%10,%11,%12,%13,%14,%15}, {%16,%17,%18,%19}, %20, p, 1, 1, 1;\n}\n"
                 : "+r"(d[0]), "+r"(d[1]), "+r"(d[2]), "+r"(d[3]), "+r"(d[4]), "+r"(d[5]), "+r"(d[6]), "+r"(d[7]), "+r"(d[8]), "+r"(d[9]),
                   "+r"(d[10]), "+r"(d[11]), "+r"(d[12]), "+r"(d[13]), "+r"(d[14]), "+r"(d[15])
                 : "r"(a.x), "r"(a.y), "r"(a.z), "r"(a.w), "l"(db), "r"(scale_d));
}
template <int TB>
__device__ __forceinline__ void wgmma_h32_rs(uint32_t (&d)[8], const uint4& a, uint64_t db, int scale_d) {
    asm volatile("{\n.reg .pred p;\nsetp.ne.b32 p, %13, 0;\n"
                 "wgmma.mma_async.sync.aligned.m64n32k16.f16.f16.f16 {%0,%1,%2,%3,%4,%5,%6,%7}, {%8,%9,%10,%11}, %12, p, 1, 1, %14;\n}\n"
                 : "+r"(d[0]), "+r"(d[1]), "+r"(d[2]), "+r"(d[3]), "+r"(d[4]), "+r"(d[5]), "+r"(d[6]), "+r"(d[7])
                 : "r"(a.x), "r"(a.y), "r"(a.z), "r"(a.w), "l"(db), "r"(scale_d), "n"(TB));
}
__device__ __forceinline__ void wgmma_s1(uint32_t (&d)[16], const uint4& a, uint64_t db, int scale_d) { wgmma_h64_rs(d, a, db, scale_d); }
__device__ __forceinline__ void wgmma_s1(uint32_t (&d)[8], const uint4& a, uint64_t db, int scale_d) { wgmma_h32_rs<1>(d, a, db, scale_d); }
__device__ __forceinline__ void wgmma_s4(float (&d)[32], const uint4& a, uint64_t db, uint32_t meta, int scale_d) {
    asm volatile("{\n.reg .pred p;\nsetp.ne.b32 p, %38, 0;\n"
                 "wgmma.mma_async.sp.sync.aligned.m64n64k32.f32.f16.f16 {%0,%1,%2,%3,%4,%5,%6,%7,%8,%9,%10,%11,%12,%13,%14,%15,%16,%17,%18,%19,%20,%21,%22,%23,%24,%25,%26,%27,%28,%29,%30,%31}, {%32,%33,%34,%35}, %36, %37, 0, p, 1, 1, 1;\n}\n"
                 : "+f"(d[0]), "+f"(d[1]), "+f"(d[2]), "+f"(d[3]), "+f"(d[4]), "+f"(d[5]), "+f"(d[6]), "+f"(d[7]), "+f"(d[8]), "+f"(d[9]), "+f"(d[10]), "+f"(d[11]), "+f"(d[12]), "+f"(d[13]), "+f"(d[14]), "+f"(d[15]), "+f"(d[16]), "+f"(d[17]), "+f"(d[18]), "+f"(d[19]), "+f"(d[20]), "+f"(d[21]), "+f"(d[22]), "+f"(d[23]), "+f"(d[24]), "+f"(d[25]), "+f"(d[26]), "+f"(d[27]), "+f"(d[28]), "+f"(d[29]), "+f"(d[30]), "+f"(d[31])
                 : "r"(a.x), "r"(a.y), "r"(a.z), "r"(a.w), "l"(db), "r"(meta), "r"(scale_d));
}
__device__ __forceinline__ void wgmma_s4(float (&d)[16], const uint4& a, uint64_t db, uint32_t meta, int scale_d) {
    asm volatile("{\n.reg .pred p;\nsetp.ne.b32 p, %22, 0;\n"
                 "wgmma.mma_async.sp.sync.aligned.m64n32k32.f32.f16.f16 {%0,%1,%2,%3,%4,%5,%6,%7,%8,%9,%10,%11,%12,%13,%14,%15}, {%16,%17,%18,%19}, %20, %21, 0, p, 1, 1, 1;\n}\n"
                 : "+f"(d[0]), "+f"(d[1]), "+f"(d[2]), "+f"(d[3]), "+f"(d[4]), "+f"(d[5]), "+f"(d[6]), "+f"(d[7]), "+f"(d[8]), "+f"(d[9]), "+f"(d[10]), "+f"(d[11]), "+f"(d[12]), "+f"(d[13]), "+f"(d[14]), "+f"(d[15])
                 : "r"(a.x), "r"(a.y), "r"(a.z), "r"(a.w), "l"(db), "r"(meta), "r"(scale_d));
}

__device__ __forceinline__ uint32_t& u4r(uint4& v, int i) { return i == 0 ? v.x : i == 1 ? v.y : i == 2 ? v.z : v.w; }

template <int NC>
__device__ __forceinline__ void fft_stage(const uint32_t (&u)[2][4], int c, uint32_t eo, int w, int lane) {
    const int mi = lane >> 3, mj = lane & 7;
    const uint32_t a = eo + (8 * w + mj) * 128 + (((4 * c + mi) ^ mj) << 4);
    stsm_x4(a, hadd(u[0][0], u[1][0]), hadd(u[0][1], u[1][1]), hadd(u[0][2], u[1][2]), hadd(u[0][3], u[1][3]));
    stsm_x4(NC == 2 ? a + 4096 : a ^ 64, hsub(u[0][0], u[1][0]), hsub(u[0][1], u[1][1]), hsub(u[0][2], u[1][2]), hsub(u[0][3], u[1][3]));
}
template <int NC>
__device__ __forceinline__ void kernel_stage(const uint4 (&ko)[2], uint32_t kt, KgShared* ks, int r, uint32_t eo, int w, int lane) {
    uint32_t u[2][2][4], sc[NC], t0[NC];
#pragma unroll
    for (int c = 0; c < NC; c++) {
        const float ci = ks->cinv[r + c], k0 = ks->tap0[r + c] + (NC == 1 ? ks->tap0[r + 1] : 0.f);
        const float mx = fmaxf(ci * (__uint_as_float(ks->kmax[r + c]) + (NC == 1 ? __uint_as_float(ks->kmax[r + 1]) : 0.f) + 0x1p-14f), fabsf(k0));
        const uint32_t e = min(max(__float_as_uint(mx) >> 23, 4u), 250u);
        const float s = __uint_as_float((253u - e) << 23), f = s * ci;
        if (w == 0 && lane == 0) ks->kexp[r + c] = e;
        sc[c] = pack2h(f, f); t0[c] = pack2h(k0 * s, 0.f);
    }
#pragma unroll
    for (int h = 0; h < 2; h++)
#pragma unroll
        for (int j = 0; j < 4; j++) {
            const uint32_t a0 = kt + (u4(ko[h], j) & 0xFFFF), a1 = kt + (u4(ko[h], j) >> 16);
#pragma unroll
            for (int c = 0; c < 2; c++)
                asm volatile("{\n.reg .b16 a, b;\nld.shared.b16 a, [%1];\nld.shared.b16 b, [%2];\nmov.b32 %0, {a, b};\n}"
                             : "=r"(u[c][h][j]) : "r"(a0 + c * KG_RES), "r"(a1 + c * KG_RES) : "memory");
            if (NC == 1) u[0][h][j] = hadd(u[0][h][j], u[1][h][j]);
#pragma unroll
            for (int c = 0; c < NC; c++) {
                u[c][h][j] = hmul(u[c][h][j], sc[c]);
                if (h + j == 0 && w == 0 && lane == 0) u[c][0][0] = __byte_perm(t0[c], u[c][0][0], 0x7610);
            }
        }
#pragma unroll
    for (int c = 0; c < NC; c++) fft_stage<NC>(u[c], c, eo, w, lane);
}

template <int NC, bool SHEAR, class Mid>
__device__ __forceinline__ void fft_forward(const uint4 (&a1)[4], const uint4 (&tw)[4], uint32_t eo, uint32_t s2, uint32_t (&X)[NC][2][8], Mid mid) {
    uint32_t dr[8 * NC], di[8 * NC];
    const uint64_t de = mkdesc(eo, 4096, 1024, 1), d2 = mkdesc(s2, 16, 1024, 1);
    wg_fence();
    wgmma_s1(dr, a1[0], de, 0);
    wgmma_s1(di, a1[2], de + (NC == 2 ? 256 : 4), 0);
    wgmma_s1(dr, a1[1], de + 128, 1);
    wgmma_s1(di, a1[3], de + (NC == 2 ? 384 : 132), 1);
    wg_commit();
    mid();
    wg_wait<0>();
#pragma unroll
    for (int c = 0; c < NC; c++) {
        uint4 zr[2], zi[2];
#pragma unroll
        for (int p = 0; p < 2; p++)
#pragma unroll
            for (int i = 0; i < 4; i++) {
                const uint32_t r = dr[8 * c + 4 * p + i], m = di[8 * c + 4 * p + i], tr = u4(tw[p], i), ti = u4(tw[2 + p], i);
                if (SHEAR) {
                    const uint32_t r1 = hfma(tr, m, r), m1 = hfma(ti, r1, m);
                    u4r(zr[p], i) = hfma(tr, m1, r1); u4r(zi[p], i) = m1;
                } else {
                    u4r(zr[p], i) = hfms(m, ti, hmul(r, tr));
                    u4r(zi[p], i) = hfma(m, tr, hmul(r, ti));
                }
            }
        wg_fence();
        wgmma_h32_rs<0>(X[c][0], zi[0], d2 + 2, 0);
        wgmma_h32_rs<0>(X[c][1], zi[1], d2 + 6, 0);
        wgmma_h32_rs<0>(X[c][0], zr[0], d2, 1);
        wgmma_h32_rs<0>(X[c][1], zr[1], d2 + 4, 1);
        wg_commit();
    }
}

template <int NC, class Idle, class Ready, class Staged>
__device__ __forceinline__ void conv_wg(int ch0, int layer, uint32_t eo, uint32_t zb, uint32_t s23, uint32_t kexp, uint32_t epoch, uint32_t st, uint32_t sbar,
                                        int warp, int lane, uint4 (&a1)[4], uint4 (&tw)[4], Idle idle, Ready ready, Staged staged TS_ARG) {
    const int wg = warp >> 2, w = warp & 3, t = 32 * w + lane, g = lane >> 2, q = lane & 3, mi = lane >> 3, mj = lane & 7;
    auto F = [](uint32_t x) { return __uint_as_float(x); };
    uint32_t KH[NC][2][8];
    TS(2);
    fft_forward<NC, false>(a1, tw, eo, s23, KH, [] {});
    named_bar(1 + wg, 128);
    uint4 a4[4];
#pragma unroll
    for (int i = 0; i < 4; i++) { tw[i] = ldg_tab(4 + i, t); if (NC == 2) a4[i] = ldg_tab(12 + i, t); }
    wg_wait<0>();
    TS(4);
    idle();
    uint2 x[NC][2][2];
    const int ra[2] = {16 * (8 * w + g) + 4 * q, 16 * (63 - 8 * w - g) + 4 * q};
    if (NC == 1) {
        uint4 s[8];
        TS(1);
#pragma unroll
        for (int i = 0; i < 8; i++) s[i] = make_uint4(layer, 0, 0, 0);
        int spin = 0;
        uint32_t bad;
        do {
            bad = 0;
#pragma unroll
            for (int i = 0; i < 8; i++)
                if (((s[i].x ^ layer) & 1u) == 0) s[i] = ld_ll4((const uint4*)(g_fs[i & 1] + 1024 * ((i >> 1) & 1) + ra[i >> 2]));
#pragma unroll
            for (int i = 0; i < 8; i++) bad |= ~(s[i].x ^ layer);
        } while ((bad & 1u) && ++spin < (1 << 18));
#pragma unroll
        for (int i = 0; i < 8; i++) sts128(st + i * 2048 + t * 16, s[i]);
        __syncwarp();
        if (lane == 0) mbar_arrive(sbar + 8 * w);
#pragma unroll
        for (int i = 0; i < 4; i++) a4[i] = ldg_tab(12 + i, t);
        TS(14);
    }
    ready();
    TS(5);
    auto xload = [&](int i) {
        const unsigned long long v = ld_ll((const unsigned long long*)(g_x1T + (size_t)(ch0 + (i >> 2)) * XP + 1024 * (i & 1) + ra[(i >> 1) & 1]));
        x[i >> 2][(i >> 1) & 1][i & 1] = make_uint2((uint32_t)v, (uint32_t)(v >> 32));
    };
#pragma unroll
    for (int i = 0; i < 4 * NC; i++) xload(i);
    if (F_PPOS == 0) staged();
    TS(6);
    for (int spin = 0; spin < (1 << 18); spin++) {
        uint32_t bad = 0;
#pragma unroll
        for (int i = 0; i < 4 * NC; i++) bad |= ~(x[i >> 2][(i >> 1) & 1][i & 1].x ^ layer);
        if (!(bad & 1u)) break;
#pragma unroll
        for (int i = 0; i < 4 * NC; i++) if (((x[i >> 2][(i >> 1) & 1][i & 1].x ^ layer) & 1u) == 0) xload(i);
    }
    __syncwarp();
    TS(26);
    if (NC == 2) mbar_wait(sbar + 8 * w, 0);
    {
        uint4 s[2][2][2];
        uint32_t u[NC][2][4];
#pragma unroll
        for (int h = 0; h < 2; h++) {
            if (NC == 1 || h == 0) {
#pragma unroll
                for (int i = 4 * h; i < (NC == 1 ? 4 * h + 4 : 8); i++) s[i >> 2][(i >> 1) & 1][i & 1] = lds128(st + i * 2048 + t * 16);
            }
            if (h == 0) TS(7);
#pragma unroll
            for (int c = 0; c < NC; c++)
#pragma unroll
                for (int j = 0; j < 4; j++) {
                    const uint4 &a = s[h][j >> 1][0], &b = s[h][j >> 1][1];
                    const uint32_t xv = (j & 1) ? x[c][h][j >> 1].y : x[c][h][j >> 1].x;
                    u[c][h][j] = pack2h(fmaf(bf_lo(xv), F(u4(a, 2 * (j & 1))), F(u4(b, 2 * (j & 1)))), fmaf(bf_hi(xv), F(u4(a, 2 * (j & 1) + 1)), F(u4(b, 2 * (j & 1) + 1))));
                }
        }
#pragma unroll
        for (int c = 0; c < NC; c++) fft_stage<NC>(u[c], c, eo, w, lane);
    }
    TS(8);
    fence_async_smem();
    TS(9);
    if (F_PPOS == 1) staged();
    named_bar(1 + wg, 128);
    uint32_t X[NC][2][8], Y[NC][2][8];
    uint32_t oscale[NC];
    fft_forward<NC, true>(a1, tw, eo, s23, X, [&] {
#pragma unroll
        for (int c = 0; c < NC; c++) oscale[c] = (lds32(kexp + 4 * c) + 3u) * 0x00800080u;
        if (layer) {
#pragma unroll
            for (int i = 0; i < 4 * NC; i++) asm volatile("mov.b32 %0, 0;\nmov.b32 %1, 0;" : "=r"(x[i >> 2][(i >> 1) & 1][i & 1].x), "=r"(x[i >> 2][(i >> 1) & 1][i & 1].y));
        }
        TS(3); if (F_PPOS == 2) staged(); if (F_STAG >= 2 && NC == 2 && wg == 1) named_bar(10 + w, 64); });
    if (F_STAG == 2 && NC == 2 && wg == 0) asm volatile("bar.arrive %0, 64;" ::"r"(10 + w) : "memory");
    TS(10);
    const uint64_t d3 = mkdesc(s23 + 4096, 16, 1024, 1);
#pragma unroll
    for (int c = 0; c < NC; c++) {
        wg_wait<NC - 1>();
        TS(11 + c);
        uint4 pr[2], pi[2];
#pragma unroll
        for (int i = 0; i < 4; i++) {
            const uint32_t er = X[c][0][i], ei = X[c][0][4 + i], orr = X[c][1][i], oi = X[c][1][4 + i];
            const uint32_t ar = KH[c][0][i], ai = KH[c][0][4 + i], br = KH[c][1][i], bi = KH[c][1][4 + i];
            u4r(pr[0], i) = hfms(bi, oi, hfma(br, orr, hfms(ai, ei, hmul(ar, er))));
            u4r(pi[0], i) = hfma(bi, orr, hfma(br, oi, hfma(ai, er, hmul(ar, ei))));
            u4r(pr[1], i) = hfms(ai, oi, hfma(ar, orr, hfms(bi, ei, hmul(br, er))));
            u4r(pi[1], i) = hfma(ai, orr, hfma(ar, oi, hfma(bi, er, hmul(br, ei))));
        }
        if (F_STAG == 3 + c && NC == 2 && wg == 0) asm volatile("bar.arrive %0, 64;" ::"r"(10 + w), "r"(pr[0].x ^ pr[1].w ^ pi[0].y ^ pi[1].z) : "memory");
        wg_fence();
        wgmma_h32_rs<0>(Y[c][0], pr[0], d3, 0);
        wgmma_h32_rs<0>(Y[c][1], pr[1], d3 + 4, 0);
        wgmma_h32_rs<0>(Y[c][0], pi[0], d3 + 2, 1);
        wgmma_h32_rs<0>(Y[c][1], pi[1], d3 + 6, 1);
        wg_commit();
    }
#pragma unroll
    for (int c = 0; c < NC; c++) {
        if (c + 1 < NC) wg_wait<1>(); else wg_wait<0>();
        TS(13 + c);
        uint32_t zr[2][4], zi[2][4];
#pragma unroll
        for (int p = 0; p < 2; p++)
#pragma unroll
            for (int i = 0; i < 4; i++) {
                const uint32_t r = Y[c][p][i], m = Y[c][p][4 + i], tr = u4(tw[p], i), ti = u4(tw[2 + p], i);
                const uint32_t r1 = hfms(tr, m, r), m1 = hfms(ti, r1, m);
                zr[i & 1][2 * p + (i >> 1)] = hfms(tr, m1, r1);
                zi[i & 1][2 * p + (i >> 1)] = m1;
            }
        const int kr = 4 * (mj >> 1) + (mj & 1) + 2 * (mj >> 2), ki = kr ^ 2;
#pragma unroll
        for (int h = 0; h < 2; h++) {
            const uint32_t a = zb + (2 * w + h) * 2048;
            stsm_x4(a + ki * 128 + (((4 * c + mi) ^ (ki & 7)) << 4), zi[h][0], zi[h][1], zi[h][2], zi[h][3]);
            stsm_x4(a + kr * 128 + (((4 * c + mi) ^ (kr & 7)) << 4), zr[h][0], zr[h][1], zr[h][2], zr[h][3]);
        }
    }
    TS(15);
    fence_async_smem();
    TS(16);
    named_bar(1 + wg, 128);
    TS(17);
    float acc[16 * NC];
    const uint64_t dz = mkdesc(zb, 4096, 1024, 1);
    wg_fence();
#pragma unroll
    for (int ks = 0; ks < 4; ks++) wgmma_s4(acc, a4[ks], dz + ks * 256, 0x44EEEE44u, ks > 0);
    wg_commit();
    uint32_t fb = ~lds32(epoch) & layer;
    const char* dst[2];
#pragma unroll
    for (int h = 0; h < 2; h++) {
        dst[h] = layer ? (const char*)&g_of[ch0 / 80][ra[h] >> 6][(ch0 % 80) * 16 + ((ra[h] >> 2) & 15)] : (const char*)(g_x2T + (size_t)ch0 * XP + ra[h]);
        asm volatile("mov.b64 %0, %0;" : "+l"(dst[h]));
    }
    wg_wait<0>();
    TS(18);
#pragma unroll
    for (int c = 0; c < NC; c++) {
        uint32_t r[2][4];
#pragma unroll
        for (int j = 0; j < 4; j++) {
            const float* d = acc + 4 * (4 * c + j);
            const uint32_t y0 = pack2(d[0] + d[2], d[1] + d[3]), y1 = pack2(d[0] - d[2], d[1] - d[3]);
            asm("fma.rn.bf16x2 %0, %1, %2, %3;" : "=r"(r[0][j]) : "r"(y0), "r"(oscale[c]), "r"((j & 1) ? x[c][0][j >> 1].y : x[c][0][j >> 1].x));
            asm("fma.rn.bf16x2 %0, %1, %2, %3;" : "=r"(r[1][j]) : "r"(y1), "r"(oscale[c]), "r"((j & 1) ? x[c][1][j >> 1].y : x[c][1][j >> 1].x));
        }
#pragma unroll
        for (int h = 0; h < 2; h++)
            asm volatile("{\n.reg .pred p;\n.reg .b128 t;\n.reg .b64 a, b;\nsetp.ne.u32 p, %5, 0;\nmov.b64 a, {%1, %2};\nmov.b64 b, {%3, %4};\nmov.b128 t, {a, b};\n"
                         "@p st.relaxed.gpu.global.b128 [%0], t;\n@!p st.global.b64 [%6], a;\n@!p st.global.b64 [%6 + 2048], b;\n}"
                         ::"l"(dst[h] + c * 256), "r"((r[h][0] & ~layer) | fb), "r"(r[h][1]), "r"(r[h][2]), "r"(r[h][3]), "r"(layer), "l"(dst[h] + c * XP * 2) : "memory");
    }
    TS(19);
}

#define Q_SCHED 3
#define Q_WAITFOR(it) (Q_SCHED == 0 ? (it) - 2 : Q_SCHED == 1 ? ((it) == 3 ? 1 : 0) : Q_SCHED == 2 ? -1 : (it) - 1)
#define Q_S0 8
#define A_HPOS 1
#define A_CSPRE 2
#define R_CONS 192
#define F_PRE 4
#define T_PF 1
#define K_CSUN 1
constexpr int K_CSU = K_CSUN;
#define G_MAP 1
#define Q_SP 2
#define X_HINT 1
#define S_FIRST 1
#define A_VLO 4
#define O_KPOS 1
#define O_PASS 0
constexpr int Q_ST = 4;
constexpr int Q_AB = 16384, Q_BB = 30720, Q_SB = Q_AB + Q_BB;
constexpr int Q_EROW = 336;
constexpr int Q_ESLOT = 8 * Q_EROW;
constexpr int Q_EOFF = Q_ST * Q_SB;
constexpr int Q_KG = 2 * Q_SB;
static_assert(3 * Q_ESLOT <= 8192 && Q_KG + KG_TABLES <= Q_EOFF + 4096, "exchange slots, kernel generation");
constexpr int F_EO = Q_EOFF, F_S23 = F_EO + 2 * 8192 + 4096, Q_KDUMP = F_S23 + 8192;
constexpr int Q_SMEM = Q_KDUMP + 6 * KG_RES + TS_SMEM;
__host__ __device__ constexpr int w_grp(int j) { return j < 7 ? 2 * Q_SB + 4096 + j * 12800 : 0; }
constexpr int W_RES = Q_AB;
__device__ __forceinline__ int o_slot(int wg, int s) { return W_RES + (((2 * s + 2) & 7) + wg) * 10240; }
__device__ __forceinline__ int w_out(int wg) { return W_RES + (2 + 3 * wg) * 10240; }
static_assert(W_RES + 8 * 10240 == w_grp(0) && w_grp(6) + 12800 <= Q_EOFF && w_grp(3) <= 3 * Q_SB, "phase W layout");

constexpr int Q_WOT = Q_EOFF + 4096;

__device__ unsigned g_epoch;
__device__ __align__(1024) unsigned g_bar[4][16][32];
__device__ __align__(1024) uint4 g_wop[8][80][10][8];
__device__ __align__(1024) uint4 g_csp[8][16][96];
__device__ __align__(1024) uint4 g_stp[16][8][64];
__device__ __align__(1024) uint4 g_sp2[16][8][8][8];
__device__ __align__(1024) uint4 g_halo[128][2][5][32];

struct Bars { uint64_t full[Q_ST], empty[Q_ST], wfull[3], ex[7], res, go, qdone, prep, ardy, hdone, fdone, idx, att[2], wfree, soon[2], st[4], kfree, staged; };
constexpr int NBAR = sizeof(Bars) / 8;
struct OBars { uint64_t full[8], ready[8], empty[8]; };
__host__ __device__ constexpr int bar_count(int i) {
#define BAR_IS(f) (i == offsetof(Bars, f) / 8)
    return (i >= 4 && i < 8) ? 16 : (BAR_IS(go) || (i >= offsetof(Bars, att) / 8 && i < offsetof(Bars, st) / 8)) ? 4 : BAR_IS(qdone) ? 8 : BAR_IS(prep) ? 96 :
           BAR_IS(hdone) ? 6 : BAR_IS(fdone) ? 3 : BAR_IS(kfree) ? 24 : BAR_IS(staged) ? 2 : 1;
}
__device__ __forceinline__ void grid_wait(const unsigned* c, int n, unsigned target, int lane) {
    const unsigned* p = c + 32 * min(lane, n - 1);
    unsigned v;
    int spin = 0;
    do { asm volatile("ld.relaxed.gpu.global.u32 %0, [%1];" : "=r"(v) : "l"(p) : "memory"); } while (!__all_sync(~0u, (int)(v - target) >= 0) && ++spin < (1 << 18));
    fence_acquire();
}
__device__ __forceinline__ void grid_arrive(unsigned* c) {
    fence_release();
    asm volatile("red.relaxed.gpu.global.add.u32 [%0], 1;" ::"l"(c) : "memory");
}

#define TMAP(n) ([] { const CUtensorMap* p_; asm volatile("{\n.reg .b64 t;\nmov.b64 t, fused_kernel_param_" #n ";\ncvta.param.u64 %0, t;\n}" : "=l"(p_)); return p_; }())
extern "C" __global__ void __launch_bounds__(384, 1)
fused_kernel(const SsmParams sp, const __grid_constant__ CUtensorMap mX0, const __grid_constant__ CUtensorMap mX1, const __grid_constant__ CUtensorMap mW,
             const __grid_constant__ CUtensorMap mWr,
             const __grid_constant__ CUtensorMap mRes0, const __grid_constant__ CUtensorMap mRes1, const __grid_constant__ CUtensorMap mOut,
             const __grid_constant__ CUtensorMap mWo, const __grid_constant__ CUtensorMap mFin, const __grid_constant__ CUtensorMap mResA) {
    extern __shared__ __align__(1024) char smraw[];
    __shared__ __align__(8) Bars s_bar[2];
    __shared__ __align__(8) OBars s_ob;
    __shared__ __align__(16) float s_cs[240], s_mean[2][64], s_rstd[2][72];
    __shared__ KgShared s_kg;
    __shared__ uint32_t s_epoch;
    const uint32_t sb = s2u(smraw);
    int tid, warp, lane, bx, rank, blk, hg, rot, c0;
    int role;
    {
        const int c = blockIdx.x >> 1, d = c - 41, r = d >= 21 ? 3 : d >= 14 ? 2 : d >= 7 ? 1 : 0;
        const int gp = c < 4 ? 0 : c <= 40 ? (c + 7) & 7 : d - 7 * r + 1;
        const int k = c < 4 ? c : c <= 40 ? (c >> 3) + (gp == 0 ? 3 : gp >= 3 && gp < 7 ? 0 : -1) : (gp >= 3 ? 5 : 4) + r;
        role = G_MAP == 1 ? 16 * k + 2 * gp + (blockIdx.x & 1) : G_MAP == 2 ? 16 * gp + 2 * k + (blockIdx.x & 1) : blockIdx.x;
    }
    auto indices = [&] {
        asm volatile("mov.u32 %0, %%tid.x;" : "=r"(tid));
        asm volatile("mov.u32 %0, %1;" : "=r"(bx) : "r"(role));
        warp = __shfl_sync(~0u, tid >> 5, 0); lane = tid & 31;
        rank = bx & 1; blk = bx & 15; hg = bx >> 4;
        const int u = ((blk >> 1) + hg) & 7;
        rot = (5 * u) >> 2; c0 = 16 * (u & 3);
    };
    indices();
    TS_DECL;
    TS_BEGIN;
#define EPOCH lds32(s2u(&s_epoch))
    int layer = 0;
    uint32_t bars = s2u(s_bar);
#define BAR(f) (bars + (uint32_t)offsetof(Bars, f))
    auto chunk = [&](int it, int s0) {
        const int i = it < s0 ? it : it - 2;
        return (it >> 1) == (s0 >> 1) ? rot + (it & 1) : i < rot ? i : i + 2;
    };
    auto osrc_of = [&](int j) { return j == 0 ? hg : j - 1 < hg ? j - 1 : j; };
    auto issue_w = [&](uint32_t bb, int it, int lay) {
        const int half = rank;
        const int s = it & (Q_ST - 1);
        const uint32_t fb = bb + 8 * s, db = sb + s * Q_SB + Q_AB + half * 15360;
        const int k0 = chunk(it, Q_SP * lay) * 64 + half * 32;
#pragma unroll
        for (int p = 0; p < 3; p++) tma2d_mc(db + p * 4096, TMAP(3), p * DM + hg * 80, k0, fb, 3);
        tma3d_mc(db + 12288, TMAP(4), hg * 80 + 64, k0, 0, fb, 3);
    };
    auto issue_x = [&](int it) {
        const int s = it & (Q_ST - 1), kc = chunk(it, Q_SP * layer);
        mbar_expect(BAR(full) + 8 * s, Q_SB);
        tma3d(sb + s * Q_SB, TMAP(1) + layer, (layer ? blk : kc) * 64, (layer ? kc : blk) * 64, 0, BAR(full) + 8 * s);
    };
    {
        KgParams kp;
        const uint32_t epoch0 = ldg32(sp.epoch);
        kgen_load(kp, bx * 5, warp, lane, sp);
        if (warp < 8) {
            cluster_arrive_relaxed();
        } else {
            if (elect_one()) {
                if (warp < 10) { prefetch_tmap(TMAP(3)); prefetch_tmap(TMAP(4)); } else prefetch_tmap(warp == 10 ? TMAP(1) : TMAP(8));
                const uint32_t b0 = bars + (warp >= 10 ? sizeof(Bars) : 0);
                if (warp & 1) {
#pragma unroll
                    for (int i = 0; i < NBAR / 2; i++) mbar_init(b0 + i * 8, bar_count(i));
                } else {
#pragma unroll
                    for (int i = NBAR / 2; i < NBAR; i++) mbar_init(b0 + i * 8, bar_count(i));
                }
                fence_mbar_init();
            }
            __syncwarp();
            cluster_arrive_relaxed();
            TS(29);
            cluster_wait();
            TS(27);
            if (elect_one()) {
                if (warp < 10) {
                    issue_w(BAR(full), warp - 8, 0);
                } else if (warp == 10) {
                    issue_x(0); issue_x(1);
                    prefetch_l2((const char*)c_fft + bx * (sizeof(c_fft) / 128), sizeof(c_fft) / 128);
                } else {
                    mbar_expect(BAR(idx), 8192 + 6400);
                    asm volatile("cp.async.bulk.tensor.4d.shared::cluster.global.mbarrier::complete_tx::bytes [%0], [%1, {0, 0, %3, %4}], [%2];"
                                 ::"r"(sb + Q_WOT), "l"(TMAP(8)), "r"(BAR(idx)), "r"(10 * hg), "r"(5 * blk) : "memory");
                    bulk_g2s(sb + F_S23, c_fft + 18 * 512, 8192, BAR(idx));
                }
            }
            __syncwarp();
            TS(30);
        }
        indices();
        kgen_tables(kp, sb + Q_KG, sb + Q_KDUMP, &s_kg, warp, lane, [&] { if (warp < 8) cluster_wait(); } TS_PASS);
        __syncwarp();
        if (lane == 0) { mbar_arrive_cta(BAR(kfree), 0); mbar_arrive_cta(BAR(kfree), 1); }
        if (warp >= 8) {
            const int t2 = tid - 256;
            float csum[10];
            if (warp < 11 && elect_one()) {
#pragma unroll
                for (int i = 0; i < 8; i++) mbar_init(s2u(&s_ob) + (warp - 8) * 64 + i * 8, warp == 10 ? 4 : 1);
                fence_mbar_init();
            }
            __syncwarp();
            if (t2 == 0) s_epoch = epoch0;
            if (t2 < 64) stg128(&g_sp2[blk][hg][0][0] + t2, make_uint4(0, 0, 0, 0));
            if (t2 >= 64 && t2 < 80) stg128(&g_of[hg][blk][640 * ((t2 >> 3) & 1) + 8 * (73 + (t2 & 6)) + 6 + (t2 & 1)], make_uint4(epoch0, epoch0, epoch0, epoch0));
            if (t2 >= 120) stg128((uint4*)g_fs + 8 * bx + t2 - 120, make_uint4(0, 0, 0, 0));
            if (t2 < 64) stg128(g_x1T + (size_t)(5 * bx + 4) * XP + 64 * (t2 >> 1) + 48 + 8 * (t2 & 1), make_uint4(0, 0, 0, 0));
#pragma unroll
            for (int i = 0; i < 3; i++)
                if (t2 + 128 * i < 320) stg128(&g_halo[bx][0][0][0] + t2 + 128 * i, make_uint4(0, 0, 0, 0));
            named_bar(13, 128);
            if (warp > 8) {
                const int hw = warp - 9, mi = lane >> 3, mj = lane & 7;
                mbar_wait(BAR(idx), 0);
                if (hw == 2 && elect_one()) { bulk_s2g(&g_wop[hg][5 * blk], sb + Q_WOT, 6400); bulk_commit(); }
                __syncwarp();
                mbar_wait(BAR(full), 0);
                mbar_wait(BAR(full) + 8, 0);
#pragma unroll
                for (int f = 0; f < 10; f++) csum[f] = 0.f;
#pragma unroll K_CSU
                for (int G = 0; G < 5; G++) {
                    const int row = c0 + 40 * rank + 8 * G + mj;
                    const uint32_t b = sb + (row >> 6) * Q_SB + Q_AB + ((row >> 5) & 1) * 15360;
                    uint32_t r[10];
                    ldsm_x4_t(r[0], r[1], r[2], r[3], b + hw * 4096 + (row & 31) * 128 + ((mi ^ mj) << 4));
                    ldsm_x4_t(r[4], r[5], r[6], r[7], b + hw * 4096 + (row & 31) * 128 + (((4 + mi) ^ mj) << 4));
                    ldsm_x2_t(r[8], r[9], b + 12288 + hw * 1024 + (row & 31) * 32 + (((mi & 1) ^ (mj >> 2)) << 4));
#pragma unroll
                    for (int f = 0; f < 10; f++) csum[f] += bf_lo(r[f]) + bf_hi(r[f]);
                }
                const int q = lane & 3;
                float t[3];
#pragma unroll
                for (int j = 0; j < 3; j++) {
                    float v[4];
#pragma unroll
                    for (int k = 0; k < 4; k++) v[k] = 4 * j + k < 10 ? csum[4 * j + k] : 0.f;
                    const float a0 = ((q & 2) ? v[2] : v[0]) + __shfl_xor_sync(~0u, (q & 2) ? v[0] : v[2], 2);
                    const float a1 = ((q & 2) ? v[3] : v[1]) + __shfl_xor_sync(~0u, (q & 2) ? v[1] : v[3], 2);
                    t[j] = ((q & 1) ? a1 : a0) + __shfl_xor_sync(~0u, (q & 1) ? a0 : a1, 1);
                }
                st_ll4(&g_csp[hg][blk][tid - 288], ~EPOCH & 1u, __float_as_uint(t[0]), __float_as_uint(t[1]), __float_as_uint(t[2]));
            }
        }
        TS(1);
    }

    uint4 fa1[4], ftw[4];
    auto conv_tables = [&] {
#pragma unroll
        for (int i = 0; i < 4; i++) { fa1[i] = ldg_tab(i, tid & 127); ftw[i] = ldg_tab(8 + i, tid & 127); }
    };
    auto conv_done = [&] {
        if (layer == 0) {
            named_bar(1 + (warp >> 2), 128);
            if ((tid & 127) == 0) {
                mbar_arrive(BAR(fdone));
                grid_arrive(g_bar[2][hg]);
            }
            __syncwarp();
        }
        TS(20);
    };
    if (warp >= 8) {
    asm volatile("setmaxnreg.dec.sync.aligned.u32 %0;" ::"n"(504 - 2 * R_CONS));
    uint32_t ophase = 0;
#pragma unroll 1
    for (; layer < 2; layer++, bars += sizeof(Bars)) {
        indices();
        TS_PHASE(2 * layer);
        if (warp == 8) {
            if (layer) {
                grid_wait(g_bar[2][0], 8, 48 * (EPOCH + 1), lane);
                mbar_wait(BAR(fdone) - sizeof(Bars), 0);
                fence_async_global();
                TS(1);
            }
            if (elect_one()) {
#pragma unroll 1
                for (int it = layer ? 0 : 2; it < 10; it++) {
                    if (it >= Q_ST) mbar_wait(BAR(empty) + 8 * (it & (Q_ST - 1)), ((it >> 2) - 1) & 1);
                    else if (layer == 0) mbar_wait(BAR(kfree), 0);
                    else if (it > 0 && Q_WAITFOR(it) >= 0) mbar_wait(BAR(full) + 8 * Q_WAITFOR(it), 0);
                    if (it == Q_ST + Q_SP * layer) mbar_wait(BAR(hdone), 0);
                    issue_x(it);
                    if (layer == 0 || it >= F_PRE) issue_w(BAR(full), it, layer);
                }
                if (T_PF) { prefetch_tmap(TMAP(5) + layer); prefetch_tmap(TMAP(7)); prefetch_tmap(TMAP(10)); }
                if (layer == 0) { mbar_wait(BAR(prep), 0); fence_async_global(); }
#pragma unroll 1
                for (int j = 0; j < 8; j++) {
                    const int b = (j + 1) >> 2;
                    const uint32_t fb = BAR(wfull) + 8 * b;
                    if (j == 0 || j == 3 || j == 7) {
                        mbar_wait(BAR(empty) + 8 * ((2 + b) & 3), b < 2);
                        TS(11 + b);
                        mbar_expect(fb, (b == 0 ? 3 : b == 1 ? 4 : 1) * 12800);
                    }
                    bulk_g2s_mc(sb + w_grp(j) + rank * 6400, &g_wop[hg][osrc_of(j) * 10 + rank * 5], 6400, fb, 3);
                }
                mbar_expect(BAR(res), 20480);
                if (layer) {
                    tma3d(sb + W_RES, TMAP(6), blk * 64, hg * 80, 0, BAR(res));
                } else {
#pragma unroll 1
                    for (int p = 0; p < 2; p++) {
                        tma3d(sb + W_RES + p * 10240, TMAP(10), hg * 80, blk * 64, p, BAR(res));
                        tma3d(sb + W_RES + p * 10240 + 8192, TMAP(5), hg * 80 + 64, blk * 64, p, BAR(res));
                    }
                }
            }
            __syncwarp();
        } else {
            const int ht = tid - 288, hw = warp - 9, mi = lane >> 3, mj = lane & 7, g = lane >> 2, q = lane & 3;
            auto F = [](uint32_t x) { return __uint_as_float(x); };
            auto U = [](float x) { return __float_as_uint(x); };
            const uint32_t lb = layer ^ 1, eb = ~EPOCH & 1u;
            mbar_wait(BAR(full) + 8 * Q_SP * layer, 0);
            mbar_wait(BAR(full) + 8 * Q_SP * layer + 8, 0);
            if (ht == 0) TSX(2, 2);
            uint32_t xf[3][20];
#pragma unroll
            for (int i = 0; i < 3; i++) {
                const int tile = min(hw + 3 * i, 7);
#pragma unroll
                for (int k = 0; k < 5; k++) {
                    const int ch = c0 + 16 * k + 8 * (mi >> 1), tok = 16 * (tile & 3) + 8 * (mi & 1);
                    const uint32_t a = sb + ((ch >> 6) + Q_SP * layer) * Q_SB + (tile >> 2) * 8192;
                    if (layer == 0) ldsm_x4(xf[i][4 * k], xf[i][4 * k + 1], xf[i][4 * k + 2], xf[i][4 * k + 3], a + (tok + mj) * 128 + ((((ch & 63) >> 3) ^ mj) << 4));
                    else ldsm_x4_t(xf[i][4 * k], xf[i][4 * k + 1], xf[i][4 * k + 2], xf[i][4 * k + 3], a + ((ch & 63) + mj) * 128 + (((tok >> 3) ^ mj) << 4));
                }
            }
            fence_async_smem();
            __syncwarp();
            if (lane == 0) { mbar_arrive_cta(BAR(hdone), 0); mbar_arrive_cta(BAR(hdone), 1); }
            if (ht == 0) TSX(2, 3);
            if (layer == 0) {
                if (hw == 2 && elect_one()) { bulk_wait(); fence_async_global(); grid_arrive(g_bar[3][hg]); }
                __syncwarp();
                mbar_wait(BAR(kfree), 0);
            }
            if (ht == 0) TSX(2, 8);
#pragma unroll 1
            for (int tile = hw; tile < 8; tile += 3) {
                float a[4] = {0.f, 0.f, 0.f, 0.f};
#pragma unroll
                for (int j = 0; j < 20; j++) {
                    const float lo = bf_lo(xf[0][j]), hi = bf_hi(xf[0][j]);
                    a[2 * (j & 1)] += lo + hi; a[2 * (j & 1) + 1] = fmaf(lo, lo, fmaf(hi, hi, a[2 * (j & 1) + 1]));
                    xf[0][j] = xf[1][j]; xf[1][j] = xf[2][j];
                }
#pragma unroll
                for (int j = 0; j < 4; j++) { a[j] += __shfl_xor_sync(~0u, a[j], 1); a[j] += __shfl_xor_sync(~0u, a[j], 2); }
                if (q == 0) st_ll4(&g_stp[blk][hg][8 * tile + g], (U(a[0]) & ~1u) | lb, U(a[1]), U(a[2]), U(a[3]));
            }
            if (ht == 0) TSX(2, 4);
            if (layer == 0) {
                float t[4] = {0.f, 0.f, 0.f, 0.f};
                uint4 v[16];
                int spin = 0;
                uint32_t bad;
                do {
                    bad = 0;
#pragma unroll
                    for (int j = 0; j < 16; j++) v[j] = ld_ll4(&g_csp[hg][j][ht]);
#pragma unroll
                    for (int j = 0; j < 16; j++) bad |= v[j].x ^ eb;
                } while ((bad & 1u) && ++spin < (1 << 18));
#pragma unroll
                for (int j = 0; j < 16; j++) { t[0] += F(v[j].y); t[1] += F(v[j].z); t[2] += F(v[j].w); }
#pragma unroll
                for (int j = 0; j < 3; j++) if (q + 4 * j < 10) s_cs[80 * hw + 20 * (g >> 1) + 2 * (q + 4 * j) + (g & 1)] = t[j];
                if (hw == 2) grid_wait(g_bar[3][0], 8, 16 * (EPOCH + 1), lane);
            }
            if (ht == 0) TSX(2, 15);
            if (ht < 80) {
                const bool halo = ht >= 64;
                const int p = halo ? (ht >> 3) & 1 : ht >> 5, i = halo ? (ht & 7) - 8 : 8 + 2 * (ht & 24) + (ht & 7);
                const uint4* src = &g_stp[halo && blk ? blk - 1 : blk][0][halo ? 32 * p + 24 + (ht & 7) : ht];
                uint4 v[8];
                int spin = 0;
                uint32_t bad;
                do {
                    bad = 0;
#pragma unroll
                    for (int j = 0; j < 8; j++) v[j] = ld_ll4(src + 64 * j);
#pragma unroll
                    for (int j = 0; j < 8; j++) bad |= v[j].x ^ lb;
                } while ((bad & 1u) && ++spin < (1 << 18));
                float t[4] = {0.f, 0.f, 0.f, 0.f};
#pragma unroll
                for (int j = 0; j < 8; j++) { t[0] += F(v[j].x); t[1] += F(v[j].y); t[2] += F(v[j].z); t[3] += F(v[j].w); }
                const uint32_t s0 = ln_finish_packed(t[0], t[1]), s1 = ln_finish_packed(t[2], t[3]);
                if (!halo) { s_mean[p][i - 8] = bf_hi(s0); s_mean[p][i] = bf_hi(s1); s_rstd[p][i] = frcp(bf_lo(s0)); }
                s_rstd[p][i + 8] = frcp(bf_lo(s1));
            }
            fence_acquire();
            mbar_arrive(BAR(prep));
            if (ht == 0) TSX(2, 5);
        }
        __syncwarp();
        indices();
        auto kstage = [&] {
            const uint4 ko[2] = {ldg_tab(16, tid & 127), ldg_tab(17, tid & 127)};
            conv_tables();
            kernel_stage<1>(ko, sb + Q_KDUMP + 4 * KG_RES, &s_kg, 4, sb + F_EO + 2 * 8192, warp & 3, lane);
            fence_async_smem();
        };
        if (O_KPOS == 0) kstage();
        {
            const int p = warp & 1;
            const uint32_t fb = EPOCH ^ layer ^ 1, ob = s2u(&s_ob) + 32 * p;
            auto fetch = [&](int j) {
                if (elect_one()) {
                    mbar_expect(ob + 8 * ((j - 1) & 3), 10240);
                    bulk_g2s(sb + o_slot(p, (j - 1) & 3), &g_of[osrc_of(j)][blk][640 * p], 10240, ob + 8 * ((j - 1) & 3));
                }
                __syncwarp();
            };
            if (warp < 10) {
                const uint32_t* pp = &g_of[osrc_of(1 + min(lane >> 2, 6))][blk][640 * p + 8 * (73 + 2 * (lane & 3)) + 7].x;
                mbar_wait(BAR(qdone), 0);
                mbar_wait(BAR(att) + 8 * p, 0);
                uint32_t miss = ~0u;
                int spin = 0;
#pragma unroll 1
                for (int j = 1; j < 8; j++) {
                    while (((miss >> (4 * j - 4)) & 15u) && ++spin < (1 << 18)) {
                        uint32_t v;
                        asm volatile("ld.relaxed.gpu.global.u32 %0, [%1];" : "=r"(v) : "l"(pp) : "memory");
                        miss = __ballot_sync(~0u, (v ^ fb) & 1u);
                        fence_async_global();
                    }
                    if (j == 1) TS(16);
                    if (j > 3) mbar_wait(ob + 128 + 8 * ((j - 1) & 3), layer);
                    fetch(j);
                }
                TS(17);
            } else {
#pragma unroll 1
                for (int j = 1, spin = 0; j < 8;) {
                    const int s = (j - 1) & 3;
                    mbar_wait(ob + 8 * s, (ophase >> s) & 1);
                    ophase ^= 1u << s;
                    const uint32_t a = sb + o_slot(p, s) + (lane >> 2) * 132 + (lane & 3) * 32;
                    uint32_t bad = 0;
#pragma unroll
                    for (int i = 0; i < 10; i++) bad |= lds32(a + i * 1024) ^ fb;
                    if (__any_sync(~0u, bad & 1u) && ++spin < (1 << 16)) { fetch(j); continue; }
                    if (lane == 0) mbar_arrive(ob + 64 + 8 * s);
                    j++;
                }
            }
        }
        TS_PHASE(2 * layer + 1);
        TS(0);
        indices();
        if (O_KPOS == 1) kstage();
        named_bar(3, 128);
        conv_wg<1>(5 * bx + 4, layer, sb + F_EO + 2 * 8192, sb + 2 * Q_SB, sb + F_S23, s2u(&s_kg.kexp[4]), s2u(&s_epoch), sb + 3 * Q_SB, BAR(st), warp, lane, fa1, ftw,
        [&] {
            if (warp == 9) {
                auto F = [](uint32_t x) { return __uint_as_float(x); };
                mbar_wait(BAR(soon) + 8 * (hg >> 2), 0);
                TS(23);
                const uint4* src = &g_sp2[blk][hg][0][0] + lane;
                uint4* dst = (uint4*)(g_fs[(lane >> 2) & 1] + 1024 * (hg >> 2) + 64 * blk + 16 * (hg & 3)) + (lane & 3);
                const bool up = lane & 8;
#pragma unroll 1
                for (int spin = 0; spin < (1 << 18); spin++) {
                    const uint4 a = ld_ll4(src), b = ld_ll4(src + 32);
                    const bool ok = !__any_sync(~0u, ~((a.x ^ layer) & (b.x ^ layer)) & 1u);
                    const float s0 = F(a.x) + F(b.x), q0 = F(a.y) + F(b.y), s1 = F(a.z) + F(b.z), q1 = F(a.w) + F(b.w);
                    float sm = (up ? s1 : s0) + __shfl_xor_sync(~0u, up ? s0 : s1, 8), sq = (up ? q1 : q0) + __shfl_xor_sync(~0u, up ? q0 : q1, 8);
                    sm += __shfl_xor_sync(~0u, sm, 16); sq += __shfl_xor_sync(~0u, sq, 16);
                    const float m = sm * (1.0f / DM), r = frsq(fmaxf(fmaf(sq, 1.0f / DM, fmaf(-m, m, 1e-5f)), 1e-5f));
                    const uint32_t v = __float_as_uint(lane & 16 ? -m * r : r);
                    const uint32_t v0 = __shfl_sync(~0u, v, 4 * lane), v1 = __shfl_sync(~0u, v, 4 * lane + 1), v2 = __shfl_sync(~0u, v, 4 * lane + 2), v3 = __shfl_sync(~0u, v, 4 * lane + 3);
                    if (ok && lane < 8) st_ll4(dst, (v0 & ~1u) | (layer ^ 1), v1, v2, v3);
                    if (ok) break;
                }
            }
            TS(25);
            mbar_wait(BAR(staged), 0);
        }, [&] { mbar_wait(BAR(ardy), 0); }, [&] {
            if (T_PF && tid == 352) prefetch_tmap(layer ? TMAP(9) : TMAP(2));
            if (layer == 0 && warp - 8 < F_PRE && elect_one()) { mbar_wait(BAR(wfree), 0); issue_w(BAR(full) + sizeof(Bars), warp - 8, 1); }
            __syncwarp();
        } TS_PASS);
        conv_done();
    }
    } else {
#pragma unroll 1
    for (; layer < 2; layer++, bars += sizeof(Bars)) {
    indices();
    TS_PHASE(2 * layer);
    const int wg = warp >> 2, w = warp & 3;
    const int mi = lane >> 3, mj = lane & 7, g = lane >> 2, q = lane & 3;
    TS(2);
    float acc[120];
#pragma unroll
    for (int i = 0; i < 120; i++) acc[i] = 0.f;
    auto release = [&](int it) {
        if (lane == 0) { mbar_arrive_cta(BAR(empty) + 8 * (it & (Q_ST - 1)), 0); mbar_arrive_cta(BAR(empty) + 8 * (it & (Q_ST - 1)), 1); }
    };
#pragma unroll 1
    for (int it = 0; it < 10; it++) {
        const int s = it & (Q_ST - 1);
        const uint32_t st = sb + s * Q_SB;
        const bool hold = wg == 1 && it == Q_S0;
        if (hold) {
            wg_wait<0>();
            release(it - 1);
            mbar_wait(BAR(go), 0);
        }
        mbar_wait(BAR(full) + 8 * (s), (it >> 2) & 1);
        if (it < 2) TS(3 + it);
        if (it == 6) TS(5);
        if (it == 9) TS(6);
        const uint64_t da = mkdesc(st + wg * 8192, 16, 1024, 1);
        const uint64_t db = mkdesc(st + Q_AB, 4096, 1024, 1);
        const uint64_t dr = mkdesc(st + Q_AB + 12288, 1024, 256, 3);
        if (layer == 0) {
            wg_fence();
#pragma unroll
            for (int ks = 0; ks < 4; ks++) {
                const int sc = 1;
                wgmma_n192<0, 1>(*(float(*)[96]) & acc[0], da + ks * 2, db + (ks >> 1) * 960 + (ks & 1) * 128, sc);
                wgmma_n48<0, 1>(*(float(*)[24]) & acc[96], da + ks * 2, dr + (ks >> 1) * 960 + (ks & 1) * 32, sc);
            }
            wg_commit();
        } else {
            wg_fence();
#pragma unroll
            for (int ks = 0; ks < 4; ks++) {
                const int sc = 1;
                wgmma_n192<1, 1>(*(float(*)[96]) & acc[0], da + ks * 128, db + (ks >> 1) * 960 + (ks & 1) * 128, sc);
                wgmma_n48<1, 1>(*(float(*)[24]) & acc[96], da + ks * 128, dr + (ks >> 1) * 960 + (ks & 1) * 32, sc);
            }
            wg_commit();
        }
        wg_wait<1>();
        if (it > 0 && !hold) release(it - 1);
    }
    if (wg == 0 && lane == 0) mbar_arrive(BAR(go));
    asm volatile("setmaxnreg.inc.sync.aligned.u32 %0;" ::"n"(R_CONS));
    mbar_wait(BAR(prep), 0);
    const uint32_t ob = layer ^ 1;
    const bool first = (blk == 0 && w == 0);
    const bool sel0 = (2 * q > g), sel1 = (2 * q + 1 > g);
    constexpr float SC = 0.22360679774997896f * 1.4426950408889634f;
    const float m0 = s_mean[wg][16 * w + g], m1 = s_mean[wg][8 + 16 * w + g];
    uint4 cs[3][5];
    auto cs_load = [&](int p) {
#pragma unroll
        for (int i = 0; i < 5; i++) cs[p][i] = lds128(s2u(&s_cs[80 * p + 20 * q + 4 * i]));
    };
    if (A_CSPRE >= 1) cs_load(1);
    if (A_CSPRE >= 2) cs_load(2);
    wg_wait<0>();
    if (A_CSPRE < 1) cs_load(1);
    if (A_CSPRE < 2) cs_load(2);
    TS(7);
    if (lane == 0) mbar_arrive(BAR(qdone));
    uint32_t ql[10], qh[10], kl[10], kh[10], vl[10], vh[10];
    auto fold = [&](int p, int f, int h) {
        const int j = (f < 8) ? 8 * p + f : 24 + 2 * p + (f - 8);
        const float c0 = __uint_as_float(u4(cs[p][f >> 1], 2 * (f & 1))), c1 = __uint_as_float(u4(cs[p][f >> 1], 2 * (f & 1) + 1));
        const float m = h ? m1 : m0;
        return pack2(fmaf(-m, c0, acc[4 * j + 2 * h]), fmaf(-m, c1, acc[4 * j + 2 * h + 1]));
    };
#pragma unroll
    for (int f = 0; f < 10; f++) { vh[f] = fold(2, f, 1); if (f < A_VLO) vl[f] = fold(2, f, 0); }
#pragma unroll
    for (int f = 0; f < 10; f++) kh[f] = fold(1, f, 1);
#pragma unroll
    for (int f = 0; f < A_VLO; f++) asm volatile("" : "+r"(vl[f]));
    {
        const uint32_t mk = w == 3 ? 1u : 0u;
        auto mark = [&](uint32_t& v) { v = (v & ~mk) | (ob & mk); };
        mark(kh[0]); mark(kh[5]); mark(vh[0]); mark(vh[4]); mark(vh[8]);
    }
    if (w == 3) {
        uint4* hp = &g_halo[bx][wg][0][lane];
        st_ll4(hp, kh[0], kh[1], kh[3], kh[4]); st_ll4(hp + 32, kh[5], kh[6], kh[8], kh[9]);
        st_ll4(hp + 64, vh[0], vh[1], vh[2], vh[3]); st_ll4(hp + 96, vh[4], vh[5], vh[6], vh[7]);
        st_ll4(hp + 128, vh[8], vh[9], kh[2], kh[7]);
    } else {
        const uint32_t a = sb + Q_EOFF + wg * 8192 + w * Q_ESLOT + mj * Q_EROW + mi * 16;
        stsm_x4(a, kh[0], kh[1], kh[3], kh[4]);
        stsm_x4(a + 64, kh[5], kh[6], kh[8], kh[9]);
        stsm_x4(a + 128, vh[0], vh[1], vh[2], vh[3]);
        stsm_x4(a + 192, vh[4], vh[5], vh[6], vh[7]);
        stsm_x4(a + 256, vh[8], vh[9], kh[2], kh[7]);
        __syncwarp();
        if (lane == 0) mbar_arrive(BAR(ex) + 8 * warp);
    }
    TS(9);
    cs_load(0);
#pragma unroll
    for (int f = 0; f < 10; f++) { kl[f] = fold(1, f, 0); if (f >= A_VLO) vl[f] = fold(2, f, 0); }
#pragma unroll
    for (int f = 0; f < 10; f++) { ql[f] = fold(0, f, 0); qh[f] = fold(0, f, 1); }
    auto rs = [&](int i) { return __uint_as_float(lds32(s2u(&s_rstd[wg][16 * w + i]))); };
    const float kx0 = rs(2 * q + (sel0 ? 0 : 8)), kx1 = rs(2 * q + (sel1 ? 1 : 9)), ky0 = rs(2 * q + (sel0 ? 8 : 16)), ky1 = rs(2 * q + (sel1 ? 9 : 17));
    const float rx = SC * rs(8 + g), ry = SC * rs(16 + g), cx0 = rx * kx0, cx1 = rx * kx1, cy0 = ry * ky0, cy1 = ry * ky1;
    uint4 hv[5];
    const uint4* hp = &g_halo[bx - 1][wg][0][lane];
    auto prev = [&] {
        if (w > 0) {
            const uint32_t a = sb + Q_EOFF + wg * 8192 + (w - 1) * Q_ESLOT + mj * Q_EROW + mi * 16;
            mbar_wait(BAR(ex) + 8 * (warp - 1), 0);
            ldsm_x4(hv[0].x, hv[0].y, hv[0].z, hv[0].w, a);
            ldsm_x4(hv[1].x, hv[1].y, hv[1].z, hv[1].w, a + 64);
            ldsm_x4_t(hv[2].x, hv[2].y, hv[2].z, hv[2].w, a + 128);
            ldsm_x4_t(hv[3].x, hv[3].y, hv[3].z, hv[3].w, a + 192);
            ldsm_x2_t(hv[4].x, hv[4].y, a + 256);
            ldsm_x2(hv[4].z, hv[4].w, a + 288 - (lane >> 4) * 32);
        } else if (blk > 0) {
#pragma unroll
            for (int f = 0; f < 5; f++) hv[f] = ld_ll4(hp + 32 * f);
        } else {
#pragma unroll
            for (int f = 0; f < 5; f++) hv[f] = make_uint4(0, 0, 0, 0);
        }
    };
    if (A_HPOS == 0) prev();
    uint32_t vt[10][2];
#pragma unroll
    for (int f = 0; f < 10; f++) { vt[f][0] = movm_t(vl[f]); vt[f][1] = movm_t(vh[f]); }
    if (A_HPOS == 1) prev();
    TS(10);
    auto FA = [](int h) { return h == 0 ? 0 : h == 1 ? 3 : h == 2 ? 5 : 8; };
    auto FH = [](int h) { return h < 2 ? 2 : 7; };
    const uint32_t pm = (sel0 ? 0xFFFFu : 0u) | (sel1 ? 0xFFFF0000u : 0u);
    auto softmax = [&](float x0, float x1, float k0, float k1) {
        float mx = fmaxf(x0, x1);
        mx = fmaxf(mx, __shfl_xor_sync(~0u, mx, 1));
        mx = fmaxf(mx, __shfl_xor_sync(~0u, mx, 2));
        x0 = ex2(x0 - mx); x1 = ex2(x1 - mx);
        float sx = x0 + x1;
        sx += __shfl_xor_sync(~0u, sx, 1);
        sx += __shfl_xor_sync(~0u, sx, 2);
        const float ix = frcp(sx);
        return pack2(x0 * k0 * ix, x1 * k1 * ix);
    };
    uint32_t qm[4][2], py[4];
    float sl[4][2];
#pragma unroll
    for (int h = 0; h < 4; h++) {
        const int fa = FA(h), fb = fa + 1, fh = FH(h);
        const bool mine = (h & 1) ? (q >= 2) : (q < 2);
        qm[h][0] = mine ? ql[fh] : 0u; qm[h][1] = mine ? qh[fh] : 0u;
        float S1[4] = {0.f, 0.f, 0.f, 0.f}, S2[4] = {0.f, 0.f, 0.f, 0.f};
        mma16816(S1, ql[fa], qh[fa], ql[fb], qh[fb], kl[fa], kl[fb]); mma1688(S1, qm[h][0], qm[h][1], kl[fh]);
        mma16816(S2, ql[fa], qh[fa], ql[fb], qh[fb], kh[fa], kh[fb]); mma1688(S2, qm[h][0], qm[h][1], kh[fh]);
        sl[h][0] = S1[0]; sl[h][1] = S1[1];
        py[h] = softmax((sel0 ? S1[2] : S2[2]) * cy0, (sel1 ? S1[3] : S2[3]) * cy1, ky0, ky1);
    }
    TS(11);
    if (w == 0 && blk > 0) {
        ll_check5(hv, hp, ob);
#pragma unroll
        for (int f = 2; f < 4; f++) hv[f] = make_uint4(movm_t(hv[f].x), movm_t(hv[f].y), movm_t(hv[f].z), movm_t(hv[f].w));
        hv[4].x = movm_t(hv[4].x); hv[4].y = movm_t(hv[4].y);
    }
    const uint32_t kp[10] = {hv[0].x, hv[0].y, hv[4].z, hv[0].z, hv[0].w, hv[1].x, hv[1].y, hv[4].w, hv[1].z, hv[1].w};
    const uint32_t vp[10] = {hv[2].x, hv[2].y, hv[2].z, hv[2].w, hv[3].x, hv[3].y, hv[3].z, hv[3].w, hv[4].x, hv[4].y};
    TS(12);
    const uint4 ko[2] = {ldg_tab(16, tid & 127), ldg_tab(17, tid & 127)};
    const float bx0 = first && sel0 ? -INFINITY : 0.f, bx1 = first && sel1 ? -INFINITY : 0.f;
    float oacc[10][4];
#pragma unroll
    for (int h = 0; h < 4; h++) {
        const int fa = FA(h), fb = fa + 1, fh = FH(h);
        const bool mine = (h & 1) ? (q >= 2) : (q < 2);
        float S0[4] = {0.f, 0.f, 0.f, 0.f};
        mma16816(S0, ql[fa], qh[fa], ql[fb], qh[fb], kp[fa], kp[fb]); mma1688(S0, qm[h][0], qm[h][1], kp[fh]);
        const uint32_t px = softmax(fmaf(sel0 ? S0[0] : sl[h][0], cx0, bx0), fmaf(sel1 ? S0[1] : sl[h][1], cx1, bx1), kx0, kx1);
#pragma unroll
        for (int i = 0; i < 3; i++) {
            const int f = (i == 0) ? fa : (i == 1) ? fb : fh;
            float O[4] = {0.f, 0.f, 0.f, 0.f};
            mma16816(O, px & ~pm, py[h] & pm, 0u, py[h] & ~pm, vt[f][0], vt[f][1]);
            mma1688(O, px & pm, 0u, vp[f]);
            if (i < 2 || !(h & 1) || mine) { oacc[f][0] = O[0]; oacc[f][1] = O[1]; oacc[f][2] = O[2]; oacc[f][3] = O[3]; }
        }
    }
    TS(13);
    float aw[40];
    {
        const uint32_t fb = EPOCH ^ ob, mk[2] = {q == 0 || mj == 2 * w, q == 0 || mj == 2 * w + 1};
        uint32_t* dst = &g_of[hg][blk][640 * wg + 16 * w].x + lane;
        uint4 of[5];
#pragma unroll
        for (int i = 0; i < 20; i++) {
            const uint32_t v = (pack2(oacc[i >> 1][2 * (i & 1)], oacc[i >> 1][2 * (i & 1) + 1]) & ~mk[i & 1]) | (fb & mk[i & 1]);
            u4r(of[i >> 2], i & 3) = v;
            asm volatile("st.relaxed.gpu.global.u32 [%0], %1;" ::"l"(dst + 256 * (i >> 1) + 32 * (i & 1)), "r"(v) : "memory");
        }
        if (lane == 0) mbar_arrive(BAR(att) + 8 * wg);
        TS(14);
        mbar_wait(BAR(wfull), 0);
        const uint64_t dm = mkdesc(sb + w_grp(0), 1280, 128, 0);
        wg_fence();
#pragma unroll
        for (int k = 0; k < 5; k++) wgmma_rs80(aw, of[k], dm + k * 160, k > 0);
        wg_commit();
    }
    const uint32_t obar = s2u(&s_ob) + 32 * wg;
    named_bar(1 + wg, 128);
    kernel_stage<2>(ko, sb + Q_KDUMP + 2 * wg * KG_RES, &s_kg, 2 * wg, sb + F_EO + wg * 8192, w, lane);
    TS(15);
    uint32_t res[20];
    mbar_wait(BAR(res), 0);
    const uint32_t ta = (8 * (mi >> 1) + mj) * 128 + (((2 * w + (mi & 1)) ^ mj) << 4);
    if (layer == 0) {
        const int tok = 16 * w + 8 * (mi & 1) + mj;
#pragma unroll
        for (int k = 0; k < 4; k++)
            ldsm_x4(res[4 * k], res[4 * k + 1], res[4 * k + 2], res[4 * k + 3], sb + W_RES + wg * 10240 + tok * 128 + (((2 * k + (mi >> 1)) ^ mj) << 4));
        ldsm_x4(res[16], res[17], res[18], res[19], sb + W_RES + wg * 10240 + 8192 + tok * 32 + (((mi >> 1) ^ (mj >> 2)) << 4));
    } else {
#pragma unroll
        for (int k = 0; k < 5; k++) ldsm_x4_t(res[4 * k], res[4 * k + 1], res[4 * k + 2], res[4 * k + 3], sb + W_RES + wg * 10240 + k * 2048 + ta);
    }
    fence_async_smem();
    __syncwarp();
    if (lane == 0) mbar_arrive(obar + 128 + 24);
    conv_tables();
    wg_wait<0>();
    if (O_PASS && wg == 1) named_bar(9, 256);
    TS(8);
#pragma unroll 1
    for (int j = 1; j < 8; j++) {
        const int s = (j - 1) & 3;
        const uint64_t da = mkdesc(sb + o_slot(wg, s), 1024, 128, 0), dm = mkdesc(sb + w_grp(j), 1280, 128, 0);
        if (s == 2) mbar_wait(BAR(wfull) + 2 * (j + 1), 0);
        mbar_wait(obar + 64 + 8 * s, s == 3 ? layer : j > 4);
        if (j == 1) TS(17);
        if (j == 5) TS(18);
        wg_fence();
#pragma unroll
        for (int k = 0; k < 5; k++) wgmma_ss80(aw, da + k * 128, dm + k * 160);
        wg_commit();
        if (O_PASS && wg == 0 && j == O_PASS) asm volatile("bar.arrive 9, 256;" ::: "memory");
        wg_wait<1>();
        if (j > 1 && j < 5 && lane == 0) mbar_arrive(obar + 128 + 8 * (j - 2));
    }
    if (lane == 0) mbar_arrive(BAR(soon) + 8 * wg);
    named_bar(1 + wg, 128);
    wg_wait<0>();
    TS(19);
#pragma unroll
    for (int i = 0; i < 20; i++) {
        const uint32_t y = pack2(aw[2 * i], aw[2 * i + 1]);
        asm("add.rn.bf16x2 %0, %0, %1;" : "+r"(res[i]) : "r"(y));
    }
    auto stage_out = [&] {
        const uint32_t mk = (g & 3) ? 0u : 0x00010001u;
#pragma unroll
        for (int k = 0; k < 5; k++) {
            uint32_t m[4];
#pragma unroll
            for (int i = 0; i < 4; i++) m[i] = (res[4 * k + i] & ~mk) | (mk & (0u - ob));
            stsm_x4_t(sb + w_out(wg) + k * 2048 + ta, m[0], m[1], m[2], m[3]);
        }
        fence_async_smem();
        named_bar(1 + wg, 128);
        if (w == 0 && elect_one()) {
            asm volatile("cp.async.bulk.tensor.2d.global.shared::cta.bulk_group [%0, {%2, %3}], [%1];"
                         ::"l"(TMAP(7)), "r"(sb + w_out(wg)), "r"(1024 * wg + 64 * blk), "r"(hg * 80) : "memory");
            bulk_commit();
            mbar_arrive(BAR(staged));
        }
        __syncwarp();
        TS(20);
    };
    if (!S_FIRST) stage_out();
    {
        float sm[4] = {0.f, 0.f, 0.f, 0.f}, d0[4] = {0.f, 0.f, 0.f, 0.f}, d1[4] = {0.f, 0.f, 0.f, 0.f};
#pragma unroll
        for (int k = 0; k < 5; k++) {
            mma16816(sm, res[4 * k], res[4 * k + 1], res[4 * k + 2], res[4 * k + 3], 0x3F803F80u, 0x3F803F80u);
            mma16816(d0, res[4 * k], res[4 * k + 1], res[4 * k + 2], res[4 * k + 3], res[4 * k], res[4 * k + 2]);
            mma16816(d1, res[4 * k], res[4 * k + 1], res[4 * k + 2], res[4 * k + 3], res[4 * k + 1], res[4 * k + 3]);
        }
        if (q == (g >> 1))
            st_ll4(&g_sp2[blk][warp][hg][g], (__float_as_uint(sm[0]) & ~1u) | ob, __float_as_uint((g & 1) ? d0[1] : d0[0]), __float_as_uint(sm[2]),
                   __float_as_uint((g & 1) ? d1[3] : d1[2]));
    }
    TS(23);
    if (S_FIRST) stage_out();
    if (layer) {
#pragma unroll
        for (int k = 0; k < 5; k++) stsm_x4_t(sb + W_RES + wg * 10240 + k * 2048 + ta, res[4 * k], res[4 * k + 1], res[4 * k + 2], res[4 * k + 3]);
    }
    TS(22);
    TS_PHASE(2 * layer + 1);
    TS(0);
    indices();
    conv_wg<2>(5 * bx + 2 * (warp >> 2), layer, sb + F_EO + (warp >> 2) * 8192, sb + (warp >> 2) * Q_SB, sb + F_S23, s2u(&s_kg.kexp[2 * (warp >> 2)]),
               s2u(&s_epoch), sb + 3 * Q_SB, BAR(st), warp, lane, fa1, ftw, [&] {
        if ((warp & 3) == 0 && elect_one()) {
            asm volatile("cp.async.bulk.wait_group.read 0;" ::: "memory");
            if (layer == 0) { mbar_arrive_cta(BAR(wfree), 0); mbar_arrive_cta(BAR(wfree), 1); }
        }
        __syncwarp();
    }, [&] {
        if (warp == 0) {
            const bf16* pp = g_x1T + (size_t)(5 * bx + 4) * XP + 64 * lane + 60;
            mbar_wait(BAR(staged), 0);
            uint32_t v;
            int spin = 0;
            if (X_HINT) do { asm volatile("ld.relaxed.gpu.global.u32 %0, [%1];" : "=r"(v) : "l"(pp) : "memory"); } while (__any_sync(~0u, ~(v ^ layer) & 1u) && ++spin < (1 << 18));
            if (lane == 0) mbar_arrive(BAR(ardy));
        } else {
            mbar_wait(BAR(ardy), 0);
        }
    }, [] {} TS_PASS);
    conv_done();
    asm volatile("setmaxnreg.dec.sync.aligned.u32 168;");
    }
    named_bar(1 + (warp >> 2), 128);
    asm volatile("setmaxnreg.dec.sync.aligned.u32 %0;" ::"n"(504 - 2 * R_CONS));
    }
    indices();
    const int cq = 4 * (warp >> 1) + (lane & 3), tg = 8 * (warp & 1) + (lane >> 2);
    const uint32_t fb = ~EPOCH & 1u;
    uint2 xr[4][2];
    __syncthreads();
    if (tid < 320) {
#pragma unroll
        for (int i = 0; i < 8; i++) {
            const int ch = 4 * cq + (i >> 1);
            asm volatile("ld.shared.v2.u32 {%0, %1}, [%2];" : "=r"(xr[i >> 1][i & 1].x), "=r"(xr[i >> 1][i & 1].y)
                         : "r"(sb + W_RES + (i & 1) * 10240 + ch * 128 + (((tg >> 1) ^ (ch & 7)) << 4) + (tg & 1) * 8) : "memory");
        }
    }
    if (tid < 320) {
        const uint4* src = &g_of[hg][blk][64 * cq + tg];
        uint4 v[4];
#pragma unroll
        for (int i = 0; i < 4; i++) v[i] = make_uint4(~fb, 0, 0, 0);
        int spin = 0;
        while (true) {
#pragma unroll
            for (int i = 0; i < 4; i++) if ((v[i].x ^ fb) & 1u) v[i] = ld_ll4(src + 16 * i);
            if (!(((v[0].x ^ fb) | (v[1].x ^ fb) | (v[2].x ^ fb) | (v[3].x ^ fb)) & 1u) || ++spin >= (1 << 18)) break;
        }
        TS(21);
#pragma unroll
        for (int i = 0; i < 16; i++) asm("add.rn.bf16x2 %0, %0, %1;" : "+r"(u4r(v[i >> 2], i & 3)) : "r"((i & 1) ? xr[i >> 2][(i >> 1) & 1].y : xr[i >> 2][(i >> 1) & 1].x));
#pragma unroll
        for (int j = 0; j < 8; j++) {
            const uint32_t sel = (j & 2) ? 0x7632 : 0x5410;
            const int k = 2 * (j & 1) + (j >> 2);
            asm volatile("st.shared.v2.u32 [%0], {%1, %2};" ::"r"(sb + 2 * Q_SB + (16 * j + tg) * 160 + cq * 8),
                         "r"(__byte_perm(u4(v[0], k), u4(v[1], k), sel)), "r"(__byte_perm(u4(v[2], k), u4(v[3], k), sel)) : "memory");
        }
        fence_async_smem();
    }
    __syncthreads();
    if (warp == 0 && elect_one()) {
        asm volatile("cp.async.bulk.tensor.3d.global.shared::cta.bulk_group [%0, {%2, %3, 0}], [%1];" ::"l"(TMAP(9)), "r"(sb + 2 * Q_SB), "r"(80 * hg), "r"(16 * blk) : "memory");
        bulk_commit();
        asm volatile("cp.async.bulk.wait_group.read 0;" ::: "memory");
    }
    if (bx == 0 && tid == 0) g_epoch = (EPOCH + 1) & 0x3FFFFFFFu;
    TS(22);
    TS_END;
}
typedef CUresult (*EncodeTiledFn)(CUtensorMap*, CUtensorMapDataType, cuuint32_t, void*, const cuuint64_t*, const cuuint64_t*, const cuuint32_t*,
                                  const cuuint32_t*, CUtensorMapInterleave, CUtensorMapSwizzle, CUtensorMapL2promotion, CUtensorMapFloatOOBfill);

static void make_map(EncodeTiledFn enc, CUtensorMap* m, const void* base, int rank, const cuuint64_t* dims, const cuuint64_t* strides,
                     const cuuint32_t* box, CUtensorMapSwizzle sw) {
    cuuint32_t es[4] = {1, 1, 1, 1};
    enc(m, CU_TENSOR_MAP_DATA_TYPE_BFLOAT16, rank, (void*)base, dims, strides, box, es, CU_TENSOR_MAP_INTERLEAVE_NONE, sw,
        sw == CU_TENSOR_MAP_SWIZZLE_128B ? CU_TENSOR_MAP_L2_PROMOTION_L2_128B : CU_TENSOR_MAP_L2_PROMOTION_NONE, CU_TENSOR_MAP_FLOAT_OOB_FILL_NONE);
}

template <typename... KArgs, typename... Args>
static void launch(void (*kern)(KArgs...), int grid, int block, int smem, int cluster, bool pdl, Args... args) {
    cudaLaunchConfig_t cfg = {};
    cfg.gridDim = dim3(grid); cfg.blockDim = dim3(block); cfg.dynamicSmemBytes = smem; cfg.stream = cudaStreamPerThread;
    cudaLaunchAttribute at[2];
    int n = 0;
    if (cluster > 1) { at[n].id = cudaLaunchAttributeClusterDimension; at[n].val.clusterDim.x = cluster; at[n].val.clusterDim.y = 1; at[n].val.clusterDim.z = 1; n++; }
    if (pdl) { at[n].id = cudaLaunchAttributeProgrammaticStreamSerialization; at[n].val.programmaticStreamSerializationAllowed = 1; n++; }
    cfg.attrs = at; cfg.numAttrs = n;
    cudaLaunchKernelEx(&cfg, kern, KArgs(args)...);
}

struct HostState {
    bool ready = false;
    const void* key[4] = {nullptr, nullptr, nullptr, nullptr};
    CUtensorMap mX[2], mRes[2], mW, mWr, mWo, mOut, mFin, mResA;
    bf16 *x1T, *x2T;
    unsigned* epoch;
};

extern "C" void kernel_launch(void* const* d_in, const int* in_sizes, int n_in, void* d_out, int out_size) {
    const bf16* x = (const bf16*)d_in[0];
    const bf16* wqkv = (const bf16*)d_in[1];
    const bf16* wo = (const bf16*)d_in[2];
    const bf16* lar = (const bf16*)d_in[4];
    const bf16* aim = (const bf16*)d_in[5];
    const bf16* cre = (const bf16*)d_in[6];
    const bf16* cim = (const bf16*)d_in[7];
    const bf16* logdt = (const bf16*)d_in[8];
    const bf16* dskip = (const bf16*)d_in[9];
    static HostState hs;
    if (!hs.ready || hs.key[0] != wqkv || hs.key[1] != wo || hs.key[2] != x || hs.key[3] != d_out) {
        void* fn = nullptr;
        cudaDriverEntryPointQueryResult qr;
        cudaGetDriverEntryPoint("cuTensorMapEncodeTiled", &fn, cudaEnableDefault, &qr);
        EncodeTiledFn enc = (EncodeTiledFn)fn;
        cudaGetSymbolAddress((void**)&hs.epoch, g_epoch);
        cudaGetSymbolAddress((void**)&hs.x1T, g_x1T);
        cudaGetSymbolAddress((void**)&hs.x2T, g_x2T);
        {
            cuuint64_t d[3] = {DM, SEQ / 2, 2}, s[2] = {DM * 4, DM * 2};
            cuuint32_t b[3] = {64, 64, 2}, ba[3] = {64, 64, 1}, br[3] = {16, 64, 1};
            make_map(enc, &hs.mX[0], x, 3, d, s, b, CU_TENSOR_MAP_SWIZZLE_128B);
            make_map(enc, &hs.mResA, x, 3, d, s, ba, CU_TENSOR_MAP_SWIZZLE_128B);
            make_map(enc, &hs.mRes[0], x, 3, d, s, br, CU_TENSOR_MAP_SWIZZLE_32B);
            cuuint64_t d2[3] = {SEQ / 2, DM, 2}, s2[2] = {XP * 2, SEQ};
            cuuint32_t b2[3] = {64, 80, 2};
            make_map(enc, &hs.mX[1], hs.x2T, 3, d2, s2, b, CU_TENSOR_MAP_SWIZZLE_128B);
            make_map(enc, &hs.mRes[1], hs.x2T, 3, d2, s2, b2, CU_TENSOR_MAP_SWIZZLE_128B);
            cuuint64_t d3[2] = {SEQ, DM};
            make_map(enc, &hs.mOut, hs.x1T, 2, d3, s2, b2, CU_TENSOR_MAP_SWIZZLE_128B);
        }
        { cuuint64_t d[2] = {3 * DM, DM}, s[1] = {3 * DM * 2}; cuuint32_t b[2] = {64, 32};
          make_map(enc, &hs.mW, wqkv, 2, d, s, b, CU_TENSOR_MAP_SWIZZLE_128B); }
        { cuuint64_t d[3] = {DM, DM, 3}, s[2] = {3 * DM * 2, DM * 2}; cuuint32_t b[3] = {16, 32, 3};
          make_map(enc, &hs.mWr, wqkv, 3, d, s, b, CU_TENSOR_MAP_SWIZZLE_32B); }
        { cuuint64_t d[4] = {8, 8, DM / 8, DM / 8}, s[3] = {DM * 2, 16, DM * 16}; cuuint32_t b[4] = {8, 8, 10, 5};
          make_map(enc, &hs.mWo, wo, 4, d, s, b, CU_TENSOR_MAP_SWIZZLE_NONE); }
        { cuuint64_t d[3] = {DM, SEQ / 8, 8}, s[2] = {DM * 16, DM * 2}; cuuint32_t b[3] = {80, 16, 8};
          make_map(enc, &hs.mFin, d_out, 3, d, s, b, CU_TENSOR_MAP_SWIZZLE_NONE); }
        cudaFuncSetAttribute(fused_kernel, cudaFuncAttributeMaxDynamicSharedMemorySize, Q_SMEM);
        hs.key[0] = wqkv; hs.key[1] = wo; hs.key[2] = x; hs.key[3] = d_out;
        hs.ready = true;
    }
    const SsmParams sp = {lar, aim, cre, cim, logdt, dskip, hs.epoch};
    launch(fused_kernel, 128, 384, Q_SMEM, 2, false, sp, hs.mX[0], hs.mX[1], hs.mW, hs.mWr, hs.mRes[0], hs.mRes[1], hs.mOut, hs.mWo, hs.mFin, hs.mResA);
}
```

```cpp
#include <cuda_runtime.h>
#include <cuda.h>
#include <cuda_bf16.h>
#include <cuda_fp16.h>
#include <stdint.h>

typedef __nv_bfloat16 bf16;

constexpr int SEQ = 2048;
constexpr int DM  = 640;
constexpr int XP  = SEQ + 64;
constexpr int NMODE = 192;

__device__ __forceinline__ uint32_t s2u(const void* p) { return (uint32_t)__cvta_generic_to_shared(p); }
__device__ __forceinline__ void mbar_init(uint32_t b, int c) { asm volatile("mbarrier.init.shared::cta.b64 [%0], %1;" ::"r"(b), "r"(c)); }
__device__ __forceinline__ void mbar_expect(uint32_t b, uint32_t bytes) { asm volatile("mbarrier.arrive.expect_tx.shared::cta.b64 _, [%0], %1;" ::"r"(b), "r"(bytes) : "memory"); }
__device__ __forceinline__ void mbar_arrive(uint32_t b) { asm volatile("mbarrier.arrive.shared::cta.b64 _, [%0];" ::"r"(b) : "memory"); }
__device__ __forceinline__ void mbar_arrive_cta(uint32_t b, uint32_t cta) {
    asm volatile("{\n.reg .b32 ra;\nmapa.shared::cluster.u32 ra, %0, %1;\nmbarrier.arrive.shared::cluster.b64 _, [ra];\n}" ::"r"(b), "r"(cta) : "memory");
}
__device__ __forceinline__ void mbar_wait(uint32_t b, uint32_t ph) {
#ifdef M_PLAIN
    asm volatile("{\n.reg .pred p;\nW: mbarrier.try_wait.parity.shared::cta.b64 p, [%0], %1;\n@!p bra W;\n}" ::"r"(b), "r"(ph) : "memory");
    return;
#endif
    asm volatile("{\n.reg .pred p;\n.reg .u32 n;\nmbarrier.try_wait.parity.shared::cta.b64 p, [%0], %1;\n@p bra D;\nmov.u32 n, 0;\n"
                 "W: mbarrier.try_wait.parity.shared::cta.b64 p, [%0], %1;\n@p bra D;\nadd.u32 n, n, 1;\nsetp.lt.u32 p, n, 4194304;\n@p bra W;\ntrap;\nD:\n}"
                 ::"r"(b), "r"(ph) : "memory");
}
__device__ __forceinline__ void fence_mbar_init() { asm volatile("fence.mbarrier_init.release.cluster;" ::: "memory"); }
__device__ __forceinline__ void cluster_sync() { asm volatile("barrier.cluster.arrive.aligned;\nbarrier.cluster.wait.aligned;" ::: "memory"); }
__device__ __forceinline__ void pdl_wait() { asm volatile("griddepcontrol.wait;" ::: "memory"); }
__device__ __forceinline__ void pdl_launch() { asm volatile("griddepcontrol.launch_dependents;" ::: "memory"); }
__device__ __forceinline__ void named_bar(int id, int n) { asm volatile("bar.sync %0, %1;" ::"r"(id), "r"(n) : "memory"); }
__device__ __forceinline__ void fence_async_smem() { asm volatile("fence.proxy.async.shared::cta;" ::: "memory"); }

__device__ __forceinline__ void tma2d(uint32_t dst, const CUtensorMap* m, int c0, int c1, uint32_t bar) {
    asm volatile("cp.async.bulk.tensor.2d.shared::cluster.global.mbarrier::complete_tx::bytes [%0], [%1, {%3, %4}], [%2];"
                 ::"r"(dst), "l"(m), "r"(bar), "r"(c0), "r"(c1) : "memory");
}
__device__ __forceinline__ void tma2d_mc(uint32_t dst, const CUtensorMap* m, int c0, int c1, uint32_t bar, uint16_t mask) {
    asm volatile("cp.async.bulk.tensor.2d.shared::cluster.global.mbarrier::complete_tx::bytes.multicast::cluster [%0], [%1, {%3, %4}], [%2], %5;"
                 ::"r"(dst), "l"(m), "r"(bar), "r"(c0), "r"(c1), "h"(mask) : "memory");
}
__device__ __forceinline__ void tma3d(uint32_t dst, const CUtensorMap* m, int c0, int c1, int c2, uint32_t bar) {
    asm volatile("cp.async.bulk.tensor.3d.shared::cluster.global.mbarrier::complete_tx::bytes [%0], [%1, {%3, %4, %5}], [%2];"
                 ::"r"(dst), "l"(m), "r"(bar), "r"(c0), "r"(c1), "r"(c2) : "memory");
}
__device__ __forceinline__ void tma3d_mc(uint32_t dst, const CUtensorMap* m, int c0, int c1, int c2, uint32_t bar, uint16_t mask) {
    asm volatile("cp.async.bulk.tensor.3d.shared::cluster.global.mbarrier::complete_tx::bytes.multicast::cluster [%0], [%1, {%3, %4, %5}], [%2], %6;"
                 ::"r"(dst), "l"(m), "r"(bar), "r"(c0), "r"(c1), "r"(c2), "h"(mask) : "memory");
}
__device__ __forceinline__ void bulk_g2s(uint32_t dst, const void* src, uint32_t bytes, uint32_t bar) {
    asm volatile("cp.async.bulk.shared::cluster.global.mbarrier::complete_tx::bytes [%0], [%1], %2, [%3];"
                 ::"r"(dst), "l"(src), "r"(bytes), "r"(bar) : "memory");
}
__device__ __forceinline__ void bulk_g2s_mc(uint32_t dst, const void* src, uint32_t bytes, uint32_t bar, uint16_t mask) {
    asm volatile("cp.async.bulk.shared::cluster.global.mbarrier::complete_tx::bytes.multicast::cluster [%0], [%1], %2, [%3], %4;"
                 ::"r"(dst), "l"(src), "r"(bytes), "r"(bar), "h"(mask) : "memory");
}
__device__ __forceinline__ void prefetch_l2(const void* p, uint32_t bytes) { asm volatile("cp.async.bulk.prefetch.L2.global [%0], %1;" ::"l"(p), "r"(bytes) : "memory"); }
__device__ __forceinline__ void prefetch_tmap(const CUtensorMap* m) { asm volatile("prefetch.tensormap [%0];" ::"l"(m) : "memory"); }

__device__ __forceinline__ void wg_fence() { asm volatile("wgmma.fence.sync.aligned;" ::: "memory"); }
__device__ __forceinline__ void wg_commit() { asm volatile("wgmma.commit_group.sync.aligned;" ::: "memory"); }
template <int N> __device__ __forceinline__ void wg_wait() { asm volatile("wgmma.wait_group.sync.aligned %0;" ::"n"(N) : "memory"); }
__device__ __forceinline__ uint64_t mkdesc(uint32_t addr, uint32_t lbo, uint32_t sbo, uint32_t mode) {
    return (uint64_t)((addr & 0x3FFFF) >> 4) | ((uint64_t)(lbo >> 4) << 16) | ((uint64_t)(sbo >> 4) << 32) | ((uint64_t)mode << 62);
}

__device__ __forceinline__ void mma16816(float (&c)[4], uint32_t a0, uint32_t a1, uint32_t a2, uint32_t a3, uint32_t b0, uint32_t b1) {
    asm("mma.sync.aligned.m16n8k16.row.col.f32.bf16.bf16.f32 {%0,%1,%2,%3},{%4,%5,%6,%7},{%8,%9},{%0,%1,%2,%3};"
                 : "+f"(c[0]), "+f"(c[1]), "+f"(c[2]), "+f"(c[3]) : "r"(a0), "r"(a1), "r"(a2), "r"(a3), "r"(b0), "r"(b1));
}
__device__ __forceinline__ void mma1688(float (&c)[4], uint32_t a0, uint32_t a1, uint32_t b0) {
    asm("mma.sync.aligned.m16n8k8.row.col.f32.bf16.bf16.f32 {%0,%1,%2,%3},{%4,%5},{%6},{%0,%1,%2,%3};"
                 : "+f"(c[0]), "+f"(c[1]), "+f"(c[2]), "+f"(c[3]) : "r"(a0), "r"(a1), "r"(b0));
}
__device__ __forceinline__ void ldsm_x4(uint32_t& r0, uint32_t& r1, uint32_t& r2, uint32_t& r3, uint32_t a) {
    asm volatile("ldmatrix.sync.aligned.m8n8.x4.shared.b16 {%0,%1,%2,%3}, [%4];" : "=r"(r0), "=r"(r1), "=r"(r2), "=r"(r3) : "r"(a) : "memory");
}
__device__ __forceinline__ void ldsm_x4_t(uint32_t& r0, uint32_t& r1, uint32_t& r2, uint32_t& r3, uint32_t a) {
    asm volatile("ldmatrix.sync.aligned.m8n8.x4.trans.shared.b16 {%0,%1,%2,%3}, [%4];" : "=r"(r0), "=r"(r1), "=r"(r2), "=r"(r3) : "r"(a) : "memory");
}
__device__ __forceinline__ void ldsm_x2(uint32_t& r0, uint32_t& r1, uint32_t a) {
    asm volatile("ldmatrix.sync.aligned.m8n8.x2.shared.b16 {%0,%1}, [%2];" : "=r"(r0), "=r"(r1) : "r"(a) : "memory");
}
__device__ __forceinline__ void ldsm_x2_t(uint32_t& r0, uint32_t& r1, uint32_t a) {
    asm volatile("ldmatrix.sync.aligned.m8n8.x2.trans.shared.b16 {%0,%1}, [%2];" : "=r"(r0), "=r"(r1) : "r"(a) : "memory");
}
__device__ __forceinline__ void stsm_x4(uint32_t a, uint32_t r0, uint32_t r1, uint32_t r2, uint32_t r3) {
    asm volatile("stmatrix.sync.aligned.m8n8.x4.shared.b16 [%0], {%1,%2,%3,%4};" ::"r"(a), "r"(r0), "r"(r1), "r"(r2), "r"(r3) : "memory");
}
__device__ __forceinline__ void stsm_x4_t(uint32_t a, uint32_t r0, uint32_t r1, uint32_t r2, uint32_t r3) {
    asm volatile("stmatrix.sync.aligned.m8n8.x4.trans.shared.b16 [%0], {%1,%2,%3,%4};" ::"r"(a), "r"(r0), "r"(r1), "r"(r2), "r"(r3) : "memory");
}
__device__ __forceinline__ void stsm_x2(uint32_t a, uint32_t r0, uint32_t r1) {
    asm volatile("stmatrix.sync.aligned.m8n8.x2.shared.b16 [%0], {%1,%2};" ::"r"(a), "r"(r0), "r"(r1) : "memory");
}
__device__ __forceinline__ uint32_t movm_t(uint32_t a) {
    uint32_t d;
    asm volatile("movmatrix.sync.aligned.m8n8.trans.b16 %0, %1;" : "=r"(d) : "r"(a));
    return d;
}
__device__ __forceinline__ uint32_t lds32(uint32_t a) { uint32_t v; asm volatile("ld.shared.u32 %0, [%1];" : "=r"(v) : "r"(a) : "memory"); return v; }
__device__ __forceinline__ uint32_t ldsv32(uint32_t a) { uint32_t v; asm volatile("ld.volatile.shared.u32 %0, [%1];" : "=r"(v) : "r"(a) : "memory"); return v; }
__device__ __forceinline__ void sts32(uint32_t a, uint32_t v) { asm volatile("st.shared.u32 [%0], %1;" ::"r"(a), "r"(v) : "memory"); }
__device__ __forceinline__ uint4 lds128(uint32_t a) { uint4 v; asm volatile("ld.shared.v4.u32 {%0,%1,%2,%3}, [%4];" : "=r"(v.x), "=r"(v.y), "=r"(v.z), "=r"(v.w) : "r"(a) : "memory"); return v; }
__device__ __forceinline__ void sts128(uint32_t a, uint4 v) { asm volatile("st.shared.v4.u32 [%0], {%1,%2,%3,%4};" ::"r"(a), "r"(v.x), "r"(v.y), "r"(v.z), "r"(v.w) : "memory"); }

__device__ __forceinline__ void stg128(void* p, uint4 v) { asm volatile("st.global.v4.u32 [%0], {%1,%2,%3,%4};" ::"l"(p), "r"(v.x), "r"(v.y), "r"(v.z), "r"(v.w) : "memory"); }

__device__ __forceinline__ uint4 ldg128(const void* p) { uint4 v; asm volatile("ld.global.v4.u32 {%0,%1,%2,%3}, [%4];" : "=r"(v.x), "=r"(v.y), "=r"(v.z), "=r"(v.w) : "l"(p) : "memory"); return v; }
__device__ __forceinline__ uint2 ldg64(const void* p) { uint2 v; asm volatile("ld.global.v2.u32 {%0,%1}, [%2];" : "=r"(v.x), "=r"(v.y) : "l"(p) : "memory"); return v; }
__device__ __forceinline__ uint32_t ldg32(const void* p) { uint32_t v; asm volatile("ld.global.u32 %0, [%1];" : "=r"(v) : "l"(p) : "memory"); return v; }

__device__ __forceinline__ uint32_t pack2(float lo, float hi) {
    uint32_t r;
    asm("cvt.rn.bf16x2.f32 %0, %1, %2;" : "=r"(r) : "f"(hi), "f"(lo));
    return r;
}
__device__ __forceinline__ float bf_lo(uint32_t v) { return __uint_as_float(v << 16); }
__device__ __forceinline__ float bf_hi(uint32_t v) { return __uint_as_float(v & 0xFFFF0000u); }
__device__ __forceinline__ float rbf(float x) { return __uint_as_float(pack2(0.f, x) & 0xFFFF0000u); }
__device__ __forceinline__ float ex2(float x) { float r; asm("ex2.approx.ftz.f32 %0, %1;" : "=f"(r) : "f"(x)); return r; }

__device__ __forceinline__ float2 ln_finish(float sum, float sumsq) {
    const float m = sum * (1.0f / DM);
    const float v = fmaxf(fmaf(sumsq, 1.0f / DM, -m * m), 0.f);
    float s, r;
    asm("sqrt.approx.ftz.f32 %0, %1;" : "=f"(s) : "f"(rbf(rbf(v) + 1e-5f)));
    asm("rcp.approx.ftz.f32 %0, %1;" : "=f"(r) : "f"(rbf(s)));
    return make_float2(m, r);
}
__device__ __forceinline__ uint32_t ln_finish_packed(float sum, float sumsq) {
    const float m = sum * (1.0f / DM);
    const float v = fmaxf(fmaf(sumsq, 1.0f / DM, -m * m), 0.f);
    float s;
    asm("sqrt.approx.ftz.f32 %0, %1;" : "=f"(s) : "f"(rbf(rbf(v) + 1e-5f)));
    return pack2(s, m);
}
__device__ __forceinline__ float frsq(float x) { float r; asm("rsqrt.approx.ftz.f32 %0, %1;" : "=f"(r) : "f"(x)); return r; }
__device__ __forceinline__ float frcp(float x) { float r; asm("rcp.approx.ftz.f32 %0, %1;" : "=f"(r) : "f"(x)); return r; }
__device__ __forceinline__ bool elect_one() {
    uint32_t p;
    asm volatile("{\n.reg .pred p;\nelect.sync _|p, 0xffffffff;\nselp.u32 %0, 1, 0, p;\n}" : "=r"(p));
    return p != 0;
}
__device__ __forceinline__ void cluster_arrive_relaxed() { asm volatile("barrier.cluster.arrive.relaxed.aligned;" ::: "memory"); }
__device__ __forceinline__ void cluster_wait() { asm volatile("barrier.cluster.wait.aligned;" ::: "memory"); }
__device__ __forceinline__ unsigned long long ld_ll(const unsigned long long* p) {
    unsigned long long v;
    asm volatile("ld.relaxed.gpu.global.b64 %0, [%1];" : "=l"(v) : "l"(p) : "memory");
    return v;
}
__device__ __forceinline__ void st_ll(unsigned long long* p, uint32_t payload, uint32_t tag) {
    const unsigned long long v = (unsigned long long)payload | ((unsigned long long)tag << 32);
    asm volatile("st.relaxed.gpu.global.b64 [%0], %1;" ::"l"(p), "l"(v) : "memory");
}
__device__ __forceinline__ uint4 ld_ll4(const uint4* p) {
    uint4 v;
    asm volatile("{\n.reg .b128 t;\n.reg .b64 a, b;\nld.relaxed.gpu.global.b128 t, [%4];\nmov.b128 {a, b}, t;\nmov.b64 {%0, %1}, a;\nmov.b64 {%2, %3}, b;\n}"
                 : "=r"(v.x), "=r"(v.y), "=r"(v.z), "=r"(v.w) : "l"(p) : "memory");
    return v;
}
__device__ __forceinline__ void st_ll4(uint4* p, uint32_t x, uint32_t y, uint32_t z, uint32_t w) {
    asm volatile("{\n.reg .b128 t;\n.reg .b64 a, b;\nmov.b64 a, {%1, %2};\nmov.b64 b, {%3, %4};\nmov.b128 t, {a, b};\nst.relaxed.gpu.global.b128 [%0], t;\n}"
                 ::"l"(p), "r"(x), "r"(y), "r"(z), "r"(w) : "memory");
}

__device__ __forceinline__ void bulk_s2g(void* dst, uint32_t src, uint32_t bytes) {
    asm volatile("cp.async.bulk.global.shared::cta.bulk_group [%0], [%1], %2;" ::"l"(dst), "r"(src), "r"(bytes) : "memory");
}
__device__ __forceinline__ void bulk_commit() { asm volatile("cp.async.bulk.commit_group;" ::: "memory"); }
__device__ __forceinline__ void bulk_wait() { asm volatile("cp.async.bulk.wait_group 0;" ::: "memory"); }
__device__ __forceinline__ void fence_async_global() { asm volatile("fence.proxy.async.global;" ::: "memory"); }
__device__ __forceinline__ void fence_release() { asm volatile("fence.release.gpu;" ::: "memory"); }
__device__ __forceinline__ void fence_acquire() { asm volatile("fence.acquire.gpu;" ::: "memory"); }
__device__ __forceinline__ void ll_check5(uint4 (&f)[5], const uint4* p, uint32_t mark) {
#define LL_LD(i, a, b, c, d) "ld.relaxed.gpu.global.b128 q, [%20 + " #i "];\nmov.b128 {u, v}, q;\nmov.b64 {%" #a ", %" #b "}, u;\nmov.b64 {%" #c ", %" #d "}, v;\n"
    asm volatile("{\n.reg .pred p;\n.reg .b32 t, n, m;\n.reg .b128 q;\n.reg .b64 u, v;\nmov.u32 n, 0x7FFFF;\n"
                 "L:\nlop3.b32 t, %0, %4, %21, 0x7E;\nlop3.b32 t, t, %8, %21, 0xF6;\nlop3.b32 t, t, %12, %21, 0xF6;\nlop3.b32 t, t, %16, %21, 0xF6;\n"
                 "shr.u32 m, n, 18;\nand.b32 t, t, m;\nsetp.ne.u32 p, t, 0;\nvote.sync.any.pred p, p, 0xffffffff;\n@!p bra.uni D;\n"
                 LL_LD(0, 0, 1, 2, 3) LL_LD(512, 4, 5, 6, 7) LL_LD(1024, 8, 9, 10, 11) LL_LD(1536, 12, 13, 14, 15) LL_LD(2048, 16, 17, 18, 19)
                 "sub.u32 n, n, 1;\nbra.uni L;\nD:\n}"
                 : "+r"(f[0].x), "+r"(f[0].y), "+r"(f[0].z), "+r"(f[0].w), "+r"(f[1].x), "+r"(f[1].y), "+r"(f[1].z), "+r"(f[1].w), "+r"(f[2].x), "+r"(f[2].y),
                   "+r"(f[2].z), "+r"(f[2].w), "+r"(f[3].x), "+r"(f[3].y), "+r"(f[3].z), "+r"(f[3].w), "+r"(f[4].x), "+r"(f[4].y), "+r"(f[4].z), "+r"(f[4].w)
                 : "l"(p), "r"(mark) : "memory");
}
template<int TA, int TB>
__device__ __forceinline__ void wgmma_n192(float (&d)[96], uint64_t da, uint64_t db, int scale_d) {
  asm volatile("{\n.reg .pred p;\nsetp.ne.b32 p, %98, 0;\n"
    "wgmma.mma_async.sync.aligned.m64n192k16.f32.bf16.bf16 "
    "{%0, %1, %2, %3, %4, %5, %6, %7, %8, %9, %10, %11, %12, %13, %14, %15, %16, %17, %18, %19, %20, %21, %22, %23, %24, %25, %26, %27, %28, %29, %30, %31, %32, %33, %34, %35, %36, %37, %38, %39, %40, %41, %42, %43, %44, %45, %46, %47, %48, %49, %50, %51, %52, %53, %54, %55, %56, %57, %58, %59, %60, %61, %62, %63, %64, %65, %66, %67, %68, %69, %70, %71, %72, %73, %74, %75, %76, %77, %78, %79, %80, %81, %82, %83, %84, %85, %86, %87, %88, %89, %90, %91, %92, %93, %94, %95}, %96, %97, p, 1, 1, %99, %100;\n}\n"
    : "+f"(d[0]), "+f"(d[1]), "+f"(d[2]), "+f"(d[3]), "+f"(d[4]), "+f"(d[5]), "+f"(d[6]), "+f"(d[7]), "+f"(d[8]), "+f"(d[9]), "+f"(d[10]), "+f"(d[11]), "+f"(d[12]), "+f"(d[13]), "+f"(d[14]), "+f"(d[15]), "+f"(d[16]), "+f"(d[17]), "+f"(d[18]), "+f"(d[19]), "+f"(d[20]), "+f"(d[21]), "+f"(d[22]), "+f"(d[23]), "+f"(d[24]), "+f"(d[25]), "+f"(d[26]), "+f"(d[27]), "+f"(d[28]), "+f"(d[29]), "+f"(d[30]), "+f"(d[31]), "+f"(d[32]), "+f"(d[33]), "+f"(d[34]), "+f"(d[35]), "+f"(d[36]), "+f"(d[37]), "+f"(d[38]), "+f"(d[39]), "+f"(d[40]), "+f"(d[41]), "+f"(d[42]), "+f"(d[43]), "+f"(d[44]), "+f"(d[45]), "+f"(d[46]), "+f"(d[47]), "+f"(d[48]), "+f"(d[49]), "+f"(d[50]), "+f"(d[51]), "+f"(d[52]), "+f"(d[53]), "+f"(d[54]), "+f"(d[55]), "+f"(d[56]), "+f"(d[57]), "+f"(d[58]), "+f"(d[59]), "+f"(d[60]), "+f"(d[61]), "+f"(d[62]), "+f"(d[63]), "+f"(d[64]), "+f"(d[65]), "+f"(d[66]), "+f"(d[67]), "+f"(d[68]), "+f"(d[69]), "+f"(d[70]), "+f"(d[71]), "+f"(d[72]), "+f"(d[73]), "+f"(d[74]), "+f"(d[75]), "+f"(d[76]), "+f"(d[77]), "+f"(d[78]), "+f"(d[79]), "+f"(d[80]), "+f"(d[81]), "+f"(d[82]), "+f"(d[83]), "+f"(d[84]), "+f"(d[85]), "+f"(d[86]), "+f"(d[87]), "+f"(d[88]), "+f"(d[89]), "+f"(d[90]), "+f"(d[91]), "+f"(d[92]), "+f"(d[93]), "+f"(d[94]), "+f"(d[95])
    : "l"(da), "l"(db), "r"(scale_d), "n"(TA), "n"(TB));
}

template<int TA, int TB>
__device__ __forceinline__ void wgmma_n48(float (&d)[24], uint64_t da, uint64_t db, int scale_d) {
  asm volatile("{\n.reg .pred p;\nsetp.ne.b32 p, %26, 0;\n"
    "wgmma.mma_async.sync.aligned.m64n48k16.f32.bf16.bf16 "
    "{%0, %1, %2, %3, %4, %5, %6, %7, %8, %9, %10, %11, %12, %13, %14, %15, %16, %17, %18, %19, %20, %21, %22, %23}, %24, %25, p, 1, 1, %27, %28;\n}\n"
    : "+f"(d[0]), "+f"(d[1]), "+f"(d[2]), "+f"(d[3]), "+f"(d[4]), "+f"(d[5]), "+f"(d[6]), "+f"(d[7]), "+f"(d[8]), "+f"(d[9]), "+f"(d[10]), "+f"(d[11]), "+f"(d[12]), "+f"(d[13]), "+f"(d[14]), "+f"(d[15]), "+f"(d[16]), "+f"(d[17]), "+f"(d[18]), "+f"(d[19]), "+f"(d[20]), "+f"(d[21]), "+f"(d[22]), "+f"(d[23])
    : "l"(da), "l"(db), "r"(scale_d), "n"(TA), "n"(TB));
}

__device__ __forceinline__ void wgmma_rs80(float (&d)[40], const uint4& a, uint64_t db, int scale_d) {
  asm volatile("{\n.reg .pred p;\nsetp.ne.b32 p, %45, 0;\n"
    "wgmma.mma_async.sync.aligned.m64n80k16.f32.bf16.bf16 {%0,%1,%2,%3,%4,%5,%6,%7,%8,%9,%10,%11,%12,%13,%14,%15,%16,%17,%18,%19,%20,%21,%22,%23,%24,%25,%26,%27,%28,%29,%30,%31,%32,%33,%34,%35,%36,%37,%38,%39}, {%40,%41,%42,%43}, %44, p, 1, 1, 1;\n}\n"
    : "+f"(d[0]), "+f"(d[1]), "+f"(d[2]), "+f"(d[3]), "+f"(d[4]), "+f"(d[5]), "+f"(d[6]), "+f"(d[7]), "+f"(d[8]), "+f"(d[9]), "+f"(d[10]), "+f"(d[11]), "+f"(d[12]), "+f"(d[13]), "+f"(d[14]), "+f"(d[15]), "+f"(d[16]), "+f"(d[17]), "+f"(d[18]), "+f"(d[19]), "+f"(d[20]), "+f"(d[21]), "+f"(d[22]), "+f"(d[23]), "+f"(d[24]), "+f"(d[25]), "+f"(d[26]), "+f"(d[27]), "+f"(d[28]), "+f"(d[29]), "+f"(d[30]), "+f"(d[31]), "+f"(d[32]), "+f"(d[33]), "+f"(d[34]), "+f"(d[35]), "+f"(d[36]), "+f"(d[37]), "+f"(d[38]), "+f"(d[39])
    : "r"(a.x), "r"(a.y), "r"(a.z), "r"(a.w), "l"(db), "r"(scale_d));
}

__device__ __forceinline__ void wgmma_ss80(float (&d)[40], uint64_t da, uint64_t db) {
  asm volatile("wgmma.mma_async.sync.aligned.m64n80k16.f32.bf16.bf16 {%0,%1,%2,%3,%4,%5,%6,%7,%8,%9,%10,%11,%12,%13,%14,%15,%16,%17,%18,%19,%20,%21,%22,%23,%24,%25,%26,%27,%28,%29,%30,%31,%32,%33,%34,%35,%36,%37,%38,%39}, %40, %41, 1, 1, 1, 0, 1;"
    : "+f"(d[0]), "+f"(d[1]), "+f"(d[2]), "+f"(d[3]), "+f"(d[4]), "+f"(d[5]), "+f"(d[6]), "+f"(d[7]), "+f"(d[8]), "+f"(d[9]), "+f"(d[10]), "+f"(d[11]), "+f"(d[12]), "+f"(d[13]), "+f"(d[14]), "+f"(d[15]), "+f"(d[16]), "+f"(d[17]), "+f"(d[18]), "+f"(d[19]), "+f"(d[20]), "+f"(d[21]), "+f"(d[22]), "+f"(d[23]), "+f"(d[24]), "+f"(d[25]), "+f"(d[26]), "+f"(d[27]), "+f"(d[28]), "+f"(d[29]), "+f"(d[30]), "+f"(d[31]), "+f"(d[32]), "+f"(d[33]), "+f"(d[34]), "+f"(d[35]), "+f"(d[36]), "+f"(d[37]), "+f"(d[38]), "+f"(d[39])
    : "l"(da), "l"(db));
}

__device__ const __align__(1024) uint32_t c_fft[11264] = {
0x2ddc2dba,0x2fe62eb5,0x2ed02eb5,0xafffaf6e,0x2e1f2dfe,0x2e3f2fbc,0x2f022ee9,0xad27af30,0x2e5e2e3f,0x1fd92b5e,0x2f302f1a,0x244ea875,0x2e992e7c,0xad96a993,0x2f5a2f46,0x2e992c32,
0xad00ad72,0xa17eac32,0xa17ea515,0xabb79cb6,0xac07ac87,0x2dfe29f1,0x1fd99648,0xafedae99,0xa9f1ab05,0x2fd42fbc,0x26a1244e,0xad96af91,0xa765a8d5,0x2aaa2e3f,0x29932875,0x2515a8d5,
0xae99adfe,0xb000aee9,0xaf6eafbc,0x2c872f30,0xaf80af1a,0xac32af02,0xae7caf02,0xaaaa217e,0xaff4afc9,0x2b5e9cb6,0xad27addc,0xaff4ae7c,0xafedb000,0x2ffc2eb5,0xab05ac5d,0xacd8af5a,
0x2c072d27,0x9fd92bb7,0xadfead00,0x2fed2e1f,0x25db2993,0xaf6eacb0,0xaf6eaed0,0x2c5d2f46,0xa5151648,0xaddcafdd,0xafffafd4,0xac321648,0xabb7a934,0x28d5a814,0xafa0afed,0xaff4af30,
0x2f302e3f,0x2fed2f1a,0x28142b5e,0x2934a875,0x30002fc9,0x26a12ddc,0xa5db1cb6,0x30002e7c,0x2f462fd4,0xaed0aa4e,0xacb0aa4e,0x29932e99,0x2d272e5e,0xae3faffc,0xaf02adfe,0xae1fa814,
0xa9f1acd8,0x26a1ab05,0x2fd42ffc,0xad96afed,0x2515a30e,0x2fff2e1f,0x2ddc2f1a,0x2c32a30e,0x2d272aaa,0x28752e7c,0x28752c32,0x2fa02f80,0x2f912e99,0xaee9a9f1,0xa8141648,0x9fd92c87,
0xafa0ae7c,0xafafaf46,0x2d002993,0xafa0ac32,0xaf91b000,0x244eac5d,0x2fbc2eb5,0xab05af5a,0xac87ae5e,0x30002dfe,0x2f6e2ffc,0x2e992814,0x1cb6a875,0x25152e1f,0x2c322e1f,0x2d722ff4,
0x27652c87,0xa9932a4e,0xaaaaadba,0xa5152c87,0xabb7a44e,0xafa0af30,0x28d59fd9,0xaff4ae5e,0xaf91ae1f,0x2814abb7,0x2ee92d00,0x1fd9ad27,0xaf5aafff,0x2fd42ed0,0x2fd42fe6,0x30002ddc,
0x2f462f6e,0x2c322fdd,0x2e7c2fdd,0xa993b000,0xab5e2934,0xafafacd8,0xad00244e,0x2f1a2dfe,0xaee9afaf,0x2f30a17e,0xadfeaff8,0xafbca30e,0x2c5da765,0xa9f12ddc,0x2d969cb6,0x2c5dacb0,
0x2bb7a993,0x2f1aa515,0x2f1a2765,0xaff4aaaa,0x2e5e2fd4,0xab052dba,0x29342f6e,0x2ee9a6a1,0xadba1fd9,0xa5dbafed,0xafddac07,0xaa4e2dfe,0xacb0aff8,0x2ddc2f02,0x9cb6ae3f,0xa765aff8,
0xaeb5af91,0xaa4eafed,0x9648ae5e,0xac5d2d4d,0x2ddca17e,0x2e7c2e3f,0x2fc92e3f,0x1cb6afa0,0x2bb72fe6,0xaff8a993,0xab5e2aaa,0x2bb72fc9,0xafbcaa4e,0x2f30a5db,0xadfeafdd,0xaee9adba,
0xacd828d5,0xaf91230e,0xaf30af02,0x2c072fa0,0xac5dafff,0x2dbaac32,0x2dbaa515,0xae99addc,0x2fc929f1,0xa9932eb5,0x2aaa2fdd,0x2fe629f1,0xa30e2dfe,0xa17eafed,0xaff8ac07,0xafaf1fd9,
0x2dfe2faf,0x28142ff8,0xae5e217e,0x2ffc230e,0xaf5aa515,0xac87af46,0xa6a1af80,0xaf5a2765,0x1cb6ae99,0x2e7c2dba,0x2fc92dba,0x2ddcac5d,0x2f1a2ee9,0xafafab05,0xad002934,0xab5e2e5e,
0x2dbaa814,0x2fdd9fd9,0x25db2f91,0x2a4eaee9,0x27652faf,0xaf4628d5,0xaf80ae1f,0xa5152faf,0xafa0addc,0x2e3fac32,0x2e3fa515,0xa17eafff,0x2dfea6a1,0xacd82dba,0x244e2f6e,0x29342fd4,
0xad27afc9,0xa30eafff,0x2faf2d72,0xad27ae7c,0x2ffc2a4e,0x28142fdd,0xae5e25db,0x2dfe2dba,0xac5d2c07,0xaa4eaf91,0x9648af30,0xaeb5acd8,0xa993aff4,0x2c322f1a,0x2e7c2f1a,0x2f462bb7,
0xae7c26a1,0xafff1648,0x2d72aa4e,0xafc926a1,0x230eaee9,0x2ff89fd9,0x217e2f91,0x2fafa814,0x2d4d2fa0,0xafed230e,0xae5eaf02,0xaf9128d5,0xb000aaaa,0x2fdda515,0x2fdd2765,0x2f6ea993,
0x9cb63000,0xacb02fd4,0xa7652fd4,0x2ddcaf5a,0x217eaffc,0x2ff4ac07,0x2875afbc,0xaff82934,0xa44e2ff4,0xadfea8d5,0xa9342fa0,0x2cd82bb7,0x25dbafe6,0x16482f46,0x29f1af80,0x25dbafc9,
0x2ff41cb6,0x2e1f2765,0x2e1f2cb0,0xa875addc,0xafbca5db,0x1fd9af5a,0xad4dad96,0xacd82fdd,0x2f5a2934,0xaeb52ee9,0x2c5d2e5e,0x3000ab05,0xaed0ab5e,0x2f80a30e,0xaaaaaf02,0xacb0ab5e,
0x25dbaffc,0x2d96afbc,0x2f5aac07,0xafdd2934,0xaaaa2fa0,0xafc92875,0xafe62875,0x29932d27,0x2d00aed0,0x28d52d72,0x2ff89cb6,0x2d00afe6,0xae5e2d96,0x2d4dafd4,0xaf91a6a1,0xafed29f1,
0xafbca17e,0xad4da875,0x1fd9aff4,0xacd82ff8,0x2e992aaa,0xaa4e2fe6,0xaa4e2fc9,0x2fd4a993,0xacb0ad96,0x2fffac87,0x2d72aeb5,0xa765ad96,0x28752f30,0xab5eac07,0xaf1a2cd8,0xae3f2f91,
0xa9342ff4,0xae5e2fa0,0xaee9a8d5,0x2b052bb7,0x2d96aed0,0x2eb59cb6,0x2c872d72,0x2d96afe6,0xaf802c5d,0x2765af6e,0xa515af6e,0xaf4625db,0x2ff8a44e,0xaff42d4d,0xa8752ffc,0xa17e2ee9,
0x2f5a244e,0x2c5d2934,0xaeb52dfe,0x3000acd8,0xacb0ad00,0x2d72aff8,0x2fffa8d5,0xa765ad00,0x217e2f80,0xaf022515,0xaf02a765,0xaf1a2f46,0x2b05afdd,0xa8142f5a,0x2c072d96,0x2d4d25db,
0x2b5eafe6,0x2f02af80,0x230e2f46,0x2b5eafc9,0xaf302d96,0xacd8a6a1,0x2c07afd4,0xaf9129f1,0x2fdda44e,0xad962ffc,0xaf5a2d4d,0xa5db2ee9,0xad72abb7,0x2e7ca17e,0x2fc9a17e,0x2fffad00,
0xaed0a5db,0xaaaaa9f1,0x2f809648,0xacb0a5db,0x28752e5e,0xaf1a2f91,0xab5ead4d,0xae3f2fed,0x2b05aff8,0x2c072875,0xa8142ff4,0x2d4d217e,0xaf6e2d72,0x2eb5afc9,0x2eb5ae7c,0x2dbaafff,
0xaf802f5a,0xafc92e99,0xafe62e99,0x2f46ad96,0x28d52b05,0xaf022fed,0x230e2cd8,0x2fa0affc,0x2fbcaf02,0xa9342d27,0x2ffcae1f,0x2c07ae3f,0xa6a1ac32,0x2a4e9cb6,0x9648ad72,0xa6a1a515,
0x28752aaa,0xa8d52cb0,0xa8d52ed0,0x2e3faf80,0x2fedaeb5,0x29349648,0x2f30aa4e,0x2814ac5d,0x1648ad4d,0x2e99acd8,0x2c87afbc,0xa9f11fd9,0xafe62d27,0x2fffafaf,0xaddc230e,0xaed02d27,
0x2fd4af30,0x2f6eae5e,0x2dbaa44e,0xa6a19fd9,0x1cb6ad27,0x2fe6aff4,0x2ed0aff4,0xad722b5e,0xafaf2cb0,0x2e1faf46,0xa8d5a993,0xafaf2ed0,0xac072f6e,0x2934ac87,0xaffc2e99,0xafbc3000,
0xa44eab5e,0x2b05ad00,0x2f91afaf,0xafbc2f1a,0xafd42d72,0x1648a765,0x1648acb0,0xafdd2fff,0xac322f5a,0xaaaa26a1,0xaf802c87,0xae7c2f5a,0x2d009fd9,0xae1f2cd8,0xad272fbc,0xabb72d4d,
0xaffc2f02,0xaee92e1f,0x244ead27,0xad4d2e3f,0xa9f12e7c,0xafdd2f80,0xaeb52aaa,0xa9f12c32,0x2d72a5db,0xafe63000,0xaed03000,0x9cb626a1,0x2fa0afbc,0xaf022f91,0x230e2b05,0x28d5a44e,
0x96482c07,0xac872d4d,0xae992b05,0x29f1a814,0x2ed0abb7,0xa9932b5e,0xaf462ff8,0x2cb0abb7,0x2f1aafff,0xa30e2765,0xa30e2cb0,0x2e1fad72,0x1fd9ac5d,0x244e9648,0x2e5eaa4e,0x2f30aeb5,
0x2ff8aed0,0x2e3faddc,0xaf022fff,0x2ff8afe6,0x2d4daf6e,0x2ee9ae99,0xa44e2c87,0x2ffcb000,0xa6a1a814,0x2f6eaf30,0x2dbaa934,0x2fd4afed,0xaf462d00,0x2fc9afa0,0x2fe6afa0,0x2f80afaf,
0x2515ac5d,0x2d72ad96,0x1cb629f1,0x2c32ac5d,0xad002814,0x2d27ad4d,0x2e1fab05,0x2bb7ac07,0xaffc2f1a,0x2cd8ad00,0x2fedafaf,0x2b05ab5e,0xadba2f80,0x2c87acb0,0x2c87aed0,0x2a4eaaaa,
0x2f802f6e,0x2fc92fdd,0x2fe62fdd,0xaf46b000,0x2fa02f91,0x2bb72e5e,0x2ff42fed,0xa8d5ad4d,0x2fbc2faf,0xa934217e,0x2ffc2ff8,0x2c07230e,0x2fd42fc9,0xaf5aad72,0x30002fff,0x2fd42e7c,
0x2bb72aaa,0x2f1a2cb0,0x2f1a2ed0,0xaff4af80,0x2cd82c5d,0x2f303000,0x2f912f5a,0xac07aeb5,0x2dba2d4d,0x25db2cd8,0x2fdd2fbc,0x2a4e9fd9,0x2e7c2e1f,0xad72a875,0x2fff2ff4,0x2fc92e1f,
0xa6a1a934,0x29f1a44e,0x2d962cd8,0xafd4adfe,0x1cb6a17e,0x2fe62e3f,0x2ed02e3f,0xad72afa0,0x28752515,0x2d272f80,0x2fa02f46,0x2875a765,0x2c072a4e,0xa93425db,0x2ffc2fdd,0x2fbc2dba,
0xae5eaf1a,0xa934ae3f,0x2b052875,0xaee9ab5e,0xac5dad72,0x2dba2765,0x2dba2cb0,0xae99afff,0xa765aa4e,0x2f802fd4,0x2f462e99,0x2515aa4e,0x230e9fd9,0x217e2cd8,0x2ff82fbc,0x2faf2d4d,
0xaffcafaf,0xaee9aff8,0x244ea17e,0xad4da30e,0xaf6eafe6,0x25dbaaaa,0x2c5d2993,0xaf6eafc9,0xad72ae99,0x2fe62dba,0x2ed02dba,0x1cb6ac5d,0xa8d5ac07,0x2bb72f30,0x2ff42f91,0x2fa02cd8,
0xadbaac07,0xafddad4d,0xa5dbab05,0xaa4e2814,0xafc9af02,0xaaaaaf1a,0x2993217e,0xafe6af02,0xafa0afff,0x2e3f2765,0x2e3f2cb0,0xa17ead72,0xad4daeb5,0x2e5e3000,0x2fed2f5a,0x2f912c5d,
0xa17e2765,0xad001cb6,0xabb7addc,0xa17e2cb0,0xad4daa4e,0xaee9afdd,0x244ea5db,0xaffcadba,0xafd4aee9,0x29f1a934,0x2d962b05,0xa6a1ae5e,0xaf46aff4,0x2fc92f1a,0x2fe62f1a,0x2f802bb7,
0x2cb02eb5,0x1cb62dba,0xaddcaf6e,0x27652eb5,0xa30e2814,0xaff8ad4d,0xa17eab05,0xafafac07,0xadfeab5e,0xa44eae3f,0x2cd82875,0xa934af1a,0xb000af80,0x2fdd2cb0,0x2fdd2ed0,0x2f6e2aaa,
0x2d723000,0x25152fd4,0x2c322fd4,0x1cb6af5a,0xae1f9fd9,0xae3faee9,0xaf02a814,0x2d272f91,0xacd8aff4,0x2ffc28d5,0xab05afa0,0xafedabb7,0x2e992515,0xad962aaa,0x2f5a2993,0x2e99a765,
0x2ff42ddc,0x2e1f2ed0,0x2e1f2fe6,0xa875afff,0xa8142c87,0xaffca9f1,0xadfe1648,0x2e5e2e99,0xaf5aaf30,0x2eb5a814,0xac5dafed,0xb000a934,0x2c32a8d5,0xa9932e3f,0x2f462875,0x2e7ca8d5,
0x2e991fd9,0x30002814,0x2f6e2ee9,0xac87af91,0x29932fa0,0xaed02875,0xacb02875,0x2f462d27,0xaff4ac32,0x2b5eaddc,0xad27afff,0xaff4a515,0x244ead96,0x1fd92fd4,0x2f3026a1,0x2e5ea9f1,
0x2814ad27,0x2dfeabb7,0x2ffc2d00,0xae5eae1f,0x2e992f80,0xaa4e2e7c,0xaa4e2c32,0x2fd42aaa,0xae7c1648,0x9cb6afdd,0xaddcafd4,0xafc91648,0xa875af91,0x2b5e2fbc,0x2f1a244e,0x2e3fab05,
0xab05aff4,0x244eafa0,0x2fbc28d5,0xaf91abb7,0x30002c32,0x26a12fff,0xa5db2ddc,0x30002515,0xaaaa2c5d,0xac32af6e,0xae7caf6e,0xaf8025db,0xad27afed,0x2e3f2dfe,0x2f021fd9,0x2e1fac07,
0xaf5aae5e,0xac5daf30,0x2eb59fd9,0xb000a44e,0x2e7ca30e,0x2ddc2e1f,0x1cb62f1a,0x2fc9a30e,0x217e2f46,0xaf02acb0,0xaf02aed0,0xaf1a2993,0xaf30ae99,0x2fbc29f1,0x2ee99648,0x2dfeac87,
0xafa0a515,0xafafa993,0x2d00aaaa,0xafa02765,0x2934ad96,0x2fed26a1,0x28142fd4,0x2f30a9f1,0x2c872fed,0xb0009fd9,0xaf6eadfe,0xae992c07,0xafffabb7,0x2fe6a17e,0x2ed0a17e,0x2ddcad00,
0xac322c87,0xaf462a4e,0x2993adba,0xae7c2c87,0xa875afed,0x2f1aab05,0x2b5e2ffc,0x2e3facd8,0x2f302e1f,0xaee92bb7,0xafbcad00,0xadfe2d27,0xaf6e9cb6,0x2eb5ac32,0x2eb5a515,0x2dbaad72,
0xaaaa2f5a,0xaed02e99,0xacb02e99,0x2f80ad96,0x2b5eaf30,0x2fafa44e,0x2d00ae5e,0xaf1a9fd9,0xac072f02,0xab05ad27,0xad4d2e1f,0x28142e3f,0x2c5daed0,0xa9f12fff,0x2d96addc,0x2c5dafe6,
0x28752f80,0xa8d52fe6,0xa8d52fc9,0x2e3faf46,0xa44eafd4,0x2f91adba,0x2b05af6e,0xafbc26a1,0x96482ffc,0xae99a44e,0xac872ee9,0x29f12d4d,0x2515aff8,0x1cb62f02,0x2d72ae3f,0x2c32aff8,
0x2eb52b05,0x2a4e2cd8,0x16482fed,0x2c5daffc,0xad72ad27,0x2cb0aff4,0x2765aff4,0xafff2b5e,0x2bb72e7c,0xaff82aaa,0xab5e2f80,0x2bb72c32,0xa814af6e,0x2b052c87,0x2d4dae99,0x2c07b000,
0x2feda8d5,0x2f30a30e,0x29342f02,0x2814afa0,0xafd49cb6,0x1648aed0,0x1648afe6,0xafdd2d72,0x2ed029f1,0xaf462eb5,0xa9932fdd,0x2cb029f1,0xad00ad4d,0x2e1f244e,0x2d27aee9,0x2bb7affc,
0x2d4daf02,0x2fbcae1f,0x2cd82d27,0x9fd9ae3f,0xaf5a2cb0,0xac87a993,0xa6a1af46,0xaf5a2ed0,0x2fffa5db,0xacb03000,0xa7653000,0x2d7226a1,0xaf1aa814,0x2fafa934,0x2d00af30,0x2b5eafed,
0x1648afbc,0x2c87affc,0x2e992934,0xa9f1ac07,0xac322faf,0xaf8028d5,0xaaaaae1f,0xae7c2faf,0x2f1aad72,0xa30e2ed0,0xa30e2fe6,0x2e1f1cb6,0xaffc26a1,0x2fedadba,0x2cd8af6e,0x2b05afd4,
0xad27ac32,0xa30ead72,0x2faf9cb6,0xad27a515,0x1fd92f6e,0xafbc2e99,0xacd8ac87,0xad4d3000,0x2c5dafbc,0x2a4e2b05,0x16482f91,0x2eb5a44e,0xaf802d00,0x2ed0afa0,0x2cb0afa0,0x2aaaafaf,
0xafe626a1,0xaddc1648,0x2fffaa4e,0xaed026a1,0x2d002c07,0xad272ffc,0xae1fa934,0xabb72fbc,0x1fd9afa0,0x2e5ea30e,0x244e2f02,0x2f30a8d5,0xadba2f46,0x2c87afe6,0x2c87afc9,0x2a4eaf80,
0xafff2d96,0xae7c2c5d,0xafc92c5d,0x2d72a9f1,0xa17e2dfe,0xaff42fbc,0xa8752ee9,0x2ff8af30,0x2fedad00,0xad4d2f1a,0x2f91ab5e,0x2e5eafaf,0x25dbae7c,0x16482993,0x29f1af46,0x25dbac32,
0xae3f2fff,0xaff82fc9,0xaff82e7c,0x2f02ad72,0x2c0725db,0xadfe2f5a,0x9fd92d96,0x2fedafdd,0x2f6eaf91,0xa6a12c07,0x2fd4acd8,0x2dbaaf30,0xa765ab5e,0x2aaaa30e,0x2993af02,0x2515ab5e,
0xa5db2dfe,0xad962ee9,0xaf5a2fbc,0x2fddaf30,0x2f46ab5e,0xa7652bb7,0x25152bb7,0x2f80aff8,0x2d00afc9,0x28d59cb6,0x2ff8addc,0x2d00ae7c,0xacd89648,0x2dfeac5d,0x2934aeb5,0x244eaa4e,
0x2c07217e,0x9fd92875,0xadfe2ff4,0x2fedaff8,0x2fddaf46,0x29f1a515,0x29f12765,0x2eb5af80,0x2515ad96,0x2ddcac87,0x2fffaeb5,0x2c32ad96,0xaf022b05,0x2fa0aee9,0x28d5ae5e,0x230ea934,
0x2f91ad00,0x2cd8ab5e,0xac072f1a,0x2f30afaf,0x2d96afc9,0x2eb5addc,0x2c879cb6,0x2d96ae7c,0xa993a6a1,0x2fc9af5a,0x2fe6af5a,0x2aaaac87,0xaff82e5e,0x2ff4affc,0x2875adfe,0x217ea814,
0x2f6eafed,0x2fd4af91,0xa6a12d4d,0x2dbaae5e,0x2515ad00,0x2fffaff8,0x2ddca8d5,0x2c32ad00,0xae1f2993,0x2fafafe6,0x2fafafc9,0x28d5aaaa,0xaf912fdd,0x2ee9af5a,0x2814ad96,0x1fd9a5db,
0x2b5eae7c,0x2f02af46,0x230e2993,0x2b5eac32,0xab059648,0x2e5eaeb5,0x2ee9ac5d,0x2934aa4e,0xafdd2e5e,0x2d96adfe,0x2f5aaffc,0x25dba814,0xaddc2faf,0x2cb0ad27,0x2765ad27,0x1cb6a30e,
0xa765a5db,0x2993a9f1,0x2aaa9648,0x2515a5db,0xaf022cd8,0x28d5a934,0x2fa0adfe,0x230ea44e,0xaf912ff8,0x2814a875,0x2ee9aff4,0x1fd9a17e,0xaa4e2ddc,0x26a1a765,0x26a1acb0,0x16489cb6,
0x2d722d96,0x25152c5d,0x2c322c5d,0x1cb6a9f1,0x2d272d4d,0xad00a814,0x2bb72c07,0x2e1f2b05,0x2cd82d00,0xaffcaf1a,0x2b052b5e,0x2fed2faf,0x2c872cb0,0xadbaaf80,0x2a4e2aaa,0x2c872ed0,
0x2e3f2ddc,0x2ff82ed0,0x2ff82fe6,0xaf02afff,0x2ee92e99,0x2d4d2f6e,0x2ffc3000,0xa44eac87,0x2f6e2f30,0xa6a12814,0x2fd42fed,0x2dba2934,0x2fc92fa0,0xaf46ad00,0x2f802faf,0x2fe62fa0,
0xac87ad4d,0x9648ac07,0x29f12814,0xae99ab05,0xa993ab5e,0x2ed02bb7,0x2cb02bb7,0xaf46aff8,0xa30ea765,0x2f1a2fff,0x2e1f2d72,0xa30eacb0,0x244e1648,0x1fd92c5d,0x2f302eb5,0x2e5e2a4e,
0xaee9ae1f,0xaffcaf02,0xad4dae3f,0x244e2d27,0xafddaf80,0xa9f1ae7c,0xa9f1ac32,0xaeb5aaaa,0xafe6b000,0x2d7225db,0x9cb6a6a1,0xaed0b000,0xaf02af91,0x2fa02fbc,0x28d5244e,0x230eab05,
0x2b052d00,0xa44e2b5e,0xafbcaf1a,0x2f912faf,0x16482765,0xafd4ad72,0xafddafff,0x16482cb0,0xaaaaa6a1,0xac32af5a,0xae7caf5a,0xaf80ac87,0xae1facd8,0x2d001fd9,0xabb7ad4d,0xad27afbc,
0x2f6e2e5e,0x2fd42f30,0xa6a11fd9,0x2dba244e,0x2fe62ff4,0x1cb62d27,0xad72ab5e,0x2ed02ff4,0x2e1f2f46,0xafafacb0,0xafafaed0,0xa8d52993,0x29342c87,0xac07af6e,0xafbcb000,0xaffcae99,
0xa8d5acb0,0x2875aaaa,0x2e3f2f80,0xa8d5aed0,0x29341648,0x2fed2eb5,0x28142c5d,0x2f302a4e,0x2e992cd8,0x16482d4d,0xa9f19fd9,0x2c872fbc,0x2fff2faf,0xafe6ad27,0xaed0ad27,0xaddca30e,
0xafc9ae99,0xaf80af5a,0x2f462d96,0xafe6ae99,0xaf02afed,0x28d5ab05,0x2fa02ffc,0x230eacd8,0xa934ad27,0x2fbc2f02,0x2c072e3f,0x2ffc2e1f,0x2a4e1cb6,0xa6a12c32,0xa6a12515,0x96482d72,
0xaaaa29f1,0xaed025db,0xacb025db,0x2f801648,0xaf1aaf91,0x2875ae5e,0xae3fafed,0xab5e2d4d,0x2c07a875,0x2b052ff8,0x2d4da17e,0xa814aff4,0x2eb52fc9,0xaf6ead72,0x2dba2fff,0x2eb52e7c,
0x2f022f80,0x2b5e2fe6,0x2b5e2fc9,0x230eaf46,0xacd826a1,0xaf30ad96,0xaf91a9f1,0x2c072fd4,0xad96affc,0x2fdd244e,0xa5dbaee9,0xaf5aad4d,0x2e7c217e,0xad722bb7,0x2fff2d00,0x2fc9217e,
0x2c5da934,0x2f5aa44e,0x30002cd8,0xaeb5adfe,0x2d722ff8,0xacb02d00,0xa7652d00,0x2fff28d5,0xaf02a515,0x217eaf80,0xaf1aaf46,0xaf022765,0xa814af5a,0x2b052fdd,0x2d4da5db,0x2c07ad96,
0xae5eafa0,0xa934aff4,0x2b05abb7,0xaee928d5,0x2eb51cb6,0x2d962ed0,0x2d962fe6,0x2c87ad72,0x27652f6e,0xaf80ac5d,0xaf46a5db,0xa5152f6e,0xaff4ad4d,0x2ff8244e,0xa17eaee9,0xa875affc,
0xad4d2875,0xafbc217e,0xacd8aff8,0x1fd92ff4,0xaa4eafe6,0x2e99aaaa,0x2fd42993,0xaa4eafc9,0x2fff2c87,0xacb02d96,0xa7652d96,0x2d722eb5,0xab5e2c07,0x2875af30,0xae3faf91,0xaf1aacd8,
0x2d962fbc,0x25db2ffc,0xafdda934,0x2f5a2c07,0xafc9a875,0xaaaaafa0,0x2993ad27,0xafe6a875,0x28d5ad72,0x2d002ed0,0x2d002fe6,0x2ff81cb6,0x2d4d2fd4,0xae5ead96,0xafeda9f1,0xaf9126a1,
0x2e1fa765,0x2ff49cb6,0xa8752ddc,0x2e1facb0,0x1fd92f5a,0xafbc25db,0xacd8afdd,0xad4d2d96,0xaeb5aee9,0x2f5aa934,0x30002b05,0x2c5dae5e,0x2f80230e,0xaed02b5e,0xacb02b5e,0xaaaa2f02,
0xacb0afd4,0x9cb6b000,0x2ddc2f5a,0xa765afd4,0x2ff42c07,0x217e2ffc,0xaff8a934,0x28752fbc,0xadfe28d5,0xa44eaff4,0x2cd8abb7,0xa934afa0,0x1648af46,0x25db2fe6,0x25db2fc9,0x29f12f80,
0xafff9648,0xae7ca6a1,0xafc9a6a1,0x2d722a4e,0x2ff81fd9,0x230e2ee9,0x2faf2814,0x217eaf91,0xafeda30e,0x2d4dafa0,0xaf91a8d5,0xae5e2f02,0x2fdd2515,0xb0002aaa,0x2f6e2993,0x2fdda765,
0xa30e2fff,0xad272fc9,0xad272e7c,0x2fafad72,0x2814afdd,0x2ffcaa4e,0x2dfeadba,0xae5ea5db,0xaa4e2f91,0xac5dac07,0xaeb52cd8,0x96482f30,0x2c32af1a,0xa9932ff4,0x2f46abb7,0x2e7caf1a,
0x2fdd1fd9,0x2dba2814,0x2a4e2ee9,0x25dbaf91,0xaf46a8d5,0x2765afaf,0xa515afaf,0xaf802e1f,0x2e3f2c32,0xafa02ddc,0xa17e2fff,0x2e3f2515,0xacd8adba,0x2dfe26a1,0x2934afd4,0x244eaf6e,
0x2814aff8,0x2dfeafaf,0x2ffca30e,0xae5ea17e,0xac872f46,0xaf5a2515,0xaf5aa765,0xa6a12f80,0x2e7cadba,0x1cb62e99,0x2ddc2c5d,0x2fc9adba,0xafaf2b05,0x2f1aaee9,0xab5eae5e,0xad00a934,
0xaf91a30e,0xacd8a8d5,0x2c07afa0,0xaf302f02,0x2dba2c32,0xac5d2fff,0xae992ddc,0x2dba2515,0xa993aeb5,0x2fc9a9f1,0x2fe6a9f1,0x2aaaafdd,0xa17e2fed,0xa30eadfe,0xafaf9fd9,0xaff82c07,
0xaa4e2fed,0xaeb52f91,0xac5dad4d,0x96482e5e,0x2e7cae3f,0x2ddc217e,0x1cb62fa0,0x2fc9ae3f,0xaff82993,0x2bb7afe6,0x2bb7afc9,0xab5eaaaa,0x2f3025db,0xafbc2a4e,0xaee92dba,0xadfe2fdd,
0x2f1a2515,0x2bb72993,0xaff42aaa,0x2f1aa765,0xab05adba,0x2e5eafd4,0x2ee926a1,0x2934af6e,0xa5db2fed,0xadba9fd9,0xaa4eadfe,0xafdd2c07,0x2ddcaf02,0xacb02ff8,0xa7652ff8,0x9cb62e3f,
0x2c32afdd,0x2f46af6e,0xa9933000,0x2e7cafdd,0xafaf2cd8,0xab5ea934,0x2f1aadfe,0xad00a44e,0x2f30217e,0xaee92faf,0xafbc230e,0xadfe2ff8,0xa9f1addc,0x2c5d2765,0x2c5d2cb0,0x2d961cb6,
0xa993aa4e,0x2765ac87,0xa515ac87,0xaaaa2dba,0xafa02f30,0xabb7244e,0xaff42e5e,0x28d51fd9,0x28142bb7,0xaf912e1f,0x1fd92d27,0x2ee9ad00,0x2fd4aed0,0xaf5a2fff,0x3000addc,0x2fd4afe6,
0xafaf2f46,0xafa02e7c,0xafa02c32,0x2d00a993,0x244e2c5d,0xaf913000,0xab052f5a,0x2fbcaeb5,0x3000adfe,0xac872e5e,0x2e99a814,0x2f6eaffc,0x2515ae1f,0x1cb62875,0x2d72aff4,0x2c32ae1f,
0x26a12b05,0xa9f12cd8,0xad962fed,0x2fd4affc,0x2fffae1f,0x2515230e,0x2c32230e,0x2ddcaf1a,0x2875ae7c,0x2d27aaaa,0x2fa0af80,0x2875ac32,0xaee929f1,0x2f91ae99,0x9fd9ac87,0xa8149648,
0x2fedaf1a,0x2f30ae3f,0x29342875,0x2814ab5e,0x26a1addc,0x3000afc9,0x3000ae7c,0xa5db9cb6,0xaed02a4e,0x2f46afd4,0x2993ae99,0xacb02a4e,0xae3f2ffc,0x2d27ae5e,0xae1f2814,0xaf022dfe,
0x9fd9abb7,0x2c07ad27,0x2fedae1f,0xadfe2d00,0xaf6e2cb0,0x25dba993,0x2c5daf46,0xaf6e2ed0,0xaddc2fdd,0xa5159648,0xac329648,0xafff2fd4,0x28d52814,0xabb72934,0xaff42f30,0xafa02fed,
0xb0002ee9,0xae992dfe,0x2c87af30,0xaf6e2fbc,0xac322f02,0xaf802f1a,0xaaaaa17e,0xae7c2f02,0x2b5e1cb6,0xaff42fc9,0xaff42e7c,0xad272ddc,0x2ffcaeb5,0xafed3000,0xacd82f5a,0xab052c5d,
0xa17e2c32,0xad002d72,0xabb71cb6,0xa17e2515,0x2dfea9f1,0xac072c87,0xafed2e99,0x1fd91648,0x2fd4afbc,0xa9f12b05,0xad962f91,0x26a1a44e,0x2aaaae3f,0xa76528d5,0x251528d5,0x2993a875,
0x2fe6aeb5,0x2ddcadba,0xafff2f6e,0x2ed0aeb5,0x2e3fafbc,0x2e1fadfe,0xad272f30,0x2f02aee9,0x1fd9ab5e,0x2e5eae3f,0x244e2875,0x2f30af1a,0xad962993,0x2e99ae7c,0x2e99ac32,0x2f5aaf46,
0x299329f1,0xa76525db,0x251525db,0x2aaa1648,0x28d52934,0xaf02acd8,0x230e244e,0x2fa02dfe,0x28142875,0xaf91aff8,0x1fd9217e,0x2ee92ff4,0x26a12765,0xaa4eaddc,0x16481cb6,0x26a12cb0,
0x2f022f46,0x2b5e2e7c,0x2b5e2c32,0x230ea993,0x2e5e2eb5,0xab051648,0x29342a4e,0x2ee92c5d,0x2d962dfe,0xafddae5e,0x25db2814,0x2f5a2ffc,0x2cb02d27,0xaddcafaf,0x1cb6230e,0x27652d27,
0x2fd42f91,0x2f6e2fed,0x2dba2e5e,0xa6a1ad4d,0x2fff2ff8,0x25152d00,0x2c322d00,0x2ddc28d5,0x2faf2fe6,0xae1fa993,0x28d52aaa,0x2faf2fc9,0x2ee92f5a,0xaf91afdd,0x1fd925db,0x28142d96,
0x2cd82b5e,0x2f912d00,0x2f302faf,0xac07af1a,0x2eb52ddc,0x2d962fc9,0x2d962e7c,0x2c871cb6,0x2fc92f5a,0xa99326a1,0x2aaa2c87,0x2fe62f5a,0x2ff42ffc,0xaff8ae5e,0x217e2814,0x28752dfe,
0x9fd9a875,0x2c07a17e,0x2fed2ff8,0xadfeaff4,0x29f12515,0x2fdd2f46,0x2eb52f80,0x29f1a765,0x2ddc2c87,0x25152d96,0x2c322d96,0x2fff2eb5,0x2fa02ee9,0xaf02ab05,0x230e2934,0x28d52e5e,
0xad96aee9,0xa5dbadfe,0x2fdd2f30,0xaf5aafbc,0xa765abb7,0x2f462b5e,0x2f802ff8,0x2515abb7,0x28d51cb6,0x2d002fc9,0x2d002e7c,0x2ff82ddc,0x2dfe2c5d,0xacd81648,0x244e2a4e,0x29342eb5,
0xaff8afc9,0xae3fafff,0x2f022d72,0xaff8ae7c,0xadfeaf5a,0x2c07a5db,0x2fed2fdd,0x9fd9ad96,0xa6a1ac07,0x2f6e2f91,0x2dba2f30,0x2fd42cd8,0x2aaa230e,0xa7652b5e,0x25152b5e,0x29932f02,
0xae7cac5d,0xafffad96,0x2d7229f1,0xafc9ac5d,0xaff4afbc,0xa17eadfe,0x2ff82f30,0xa875aee9,0xad4daf1a,0x2fed2d00,0x2e5e2faf,0x2f912b5e,0x1648a993,0x25db2e7c,0x25db2c32,0x29f12f46,
0xaddc9648,0xafe6a6a1,0xaed0a6a1,0x2fff2a4e,0xad27affc,0x2d00ac07,0xabb7afbc,0xae1f2934,0x2e5e230e,0x1fd92fa0,0x2f3028d5,0x244eaf02,0x2c872fe6,0xadbaaf46,0x2a4e2f80,0x2c872fc9,
0xa30e2d72,0xad272c32,0xad272515,0x2faf1cb6,0xafbcae99,0x1fd9af6e,0xad4db000,0xacd82c87,0x2a4eab05,0x2c5d2fbc,0x2eb5244e,0x1648af91,0x2ed02fa0,0xaf80ad00,0x2aaa2faf,0x2cb02fa0,
0x2c872ffc,0x16482fbc,0xa9f12c07,0x2e99a934,0xaf80a8d5,0xac32afaf,0xae7cafaf,0xaaaa2e1f,0xa30eaed0,0x2f1a2d72,0x2e1f9cb6,0xa30eafe6,0x2fed2dba,0xaffca6a1,0x2b052fd4,0x2cd82f6e,
0x2fbc2e1f,0x2d4d2f02,0x9fd92e3f,0x2cd8ad27,0xac872993,0xaf5aacb0,0xaf5aaed0,0xa6a12f46,0xacb0b000,0x2fff25db,0x2d72a6a1,0xa765b000,0x2faf2934,0xaf1a2814,0x2b5e2fed,0x2d002f30,
0x2f30230e,0x2fed28d5,0x28142fa0,0x2934af02,0x16482ed0,0xafd41cb6,0xafddad72,0x16482fe6,0xaf46aeb5,0x2ed0a9f1,0x2cb0a9f1,0xa993afdd,0x2e1fa44e,0xad002d4d,0x2bb72ffc,0x2d272ee9,
0x2a4eacd8,0x2eb5ab05,0x2c5d2ffc,0x1648afed,0x2cb02ff4,0xad722d27,0xafffab5e,0x27652ff4,0xaff8aaaa,0x2bb7ae7c,0x2bb7ac32,0xab5eaf80,0x2b05ac87,0xa8142f6e,0x2c073000,0x2d4d2e99,
0xa8d5afe6,0x2875af80,0x2e3f2f46,0xa8d5afc9,0x2f912dba,0xa44e2fd4,0xafbca6a1,0x2b052f6e,0xae99244e,0x9648affc,0x29f1ad4d,0xac87aee9,0x1cb6af02,0x25152ff8,0x2c322ff8,0x2d722e3f,
0xaed0ae99,0xaaaaaf5a,0x2f802d96,0xacb0ae99,0x2faf244e,0x2b5e2f30,0xaf1a1fd9,0x2d002e5e,0xab052d27,0xac07af02,0x2814ae3f,0xad4dae1f,0xa9f1afff,0x2c5d2ed0,0x2c5d2fe6,0x2d962ddc,
0xaf46aa4e,0xac32ac87,0xae7cac87,0x29932dba,0x2f1a2b05,0xa8752fed,0x2e3f2cd8,0x2b5eaffc,0xaee9abb7,0x2f30ae1f,0xadfead27,0xafbc2d00,0x2eb52c32,0xaf6e1cb6,0x2dba2d72,0x2eb52515,
0xafaf2993,0xafa02515,0xafa0a765,0x2d002aaa,0x2feda6a1,0x29342d96,0x2f3029f1,0x2814afd4,0xb0001fd9,0x2c87afed,0xae99ac07,0xaf6e2dfe,0x2fe6217e,0xafff2bb7,0x2ddc2d00,0x2ed0217e,
0xac5d2f30,0xaf5a2e5e,0xb000244e,0x2eb51fd9,0x2ddcae1f,0x2e7c230e,0x2fc9230e,0x1cb6af1a,0xaf022cb0,0x217eaf46,0xaf1aa993,0xaf022ed0,0x2fbca9f1,0xaf302e99,0x2dfe2c87,0x2ee91648,
0x244e2fa0,0xab052ff4,0xaf912bb7,0x2fbca8d5,0x26a1afff,0x3000ac32,0x3000a515,0xa5dbaddc,0xac322f6e,0xaaaaac5d,0xaf80a5db,0xae7c2f6e,0x2e3fadfe,0xad272fed,0x2e1f2c07,0x2f029fd9,
0x2dfe2bb7,0x28142d27,0xae5e2e1f,0x2ffcad00,0xaa4eae7c,0x2e99af80,0x2fd4aaaa,0xaa4eac32,0x9cb62fdd,0xae7c9648,0xafc99648,0xaddc2fd4,0x2b5eafbc,0xa8752f91,0x2e3f2b05,0x2f1aa44e,
0x3000a814,0x2e999fd9,0xac872f91,0x2f6eaee9,0xaed0a875,0x2993afa0,0x2f46ad27,0xacb0a875,0x2b5e2ddc,0xaff42c32,0xaff42515,0xad272fff,0x1fd9afd4,0x244e2d96,0x2e5e29f1,0x2f30a6a1,
0x2e1faed0,0x2ff4addc,0xa8752fff,0x2e1fafe6,0xaffc29f1,0xa814ac87,0x2e5eae99,0xadfe9648,0x2eb52814,0xaf5a2f30,0xb0002934,0xac5d2fed,0xa993ae3f,0x2c3228d5,0x2e7c28d5,0x2f46a875,
0x2515afd4,0x2d72b000,0x1cb62f5a,0x2c32afd4,0xae3f2ee9,0xae1f1fd9,0x2d27af91,0xaf022814,0x2ffca8d5,0xacd82ff4,0xafed2bb7,0xab052fa0,0xad96aaaa,0x2e99a515,0x2e992765,0x2f5aa993,
0x1cb6adba,0x2cb0aeb5,0x2765aeb5,0xaddc2f6e,0xaff82d4d,0xa30ea814,0xafaf2c07,0xa17e2b05,0xa44e2e3f,0xadfe2b5e,0xa9342f1a,0x2cd8a875,0x2fddacb0,0xb0002f80,0x2f6eaaaa,0x2fddaed0,
0xad009cb6,0xa17ea765,0xa17eacb0,0xabb72ddc,0xaee92fdd,0xad4d2a4e,0xaffc2dba,0x244e25db,0x29f12934,0xafd42ee9,0xa6a12e5e,0x2d96ab05,0x2fc9af1a,0xaf462ff4,0x2f80abb7,0x2fe6af1a,
0xafdd2d4d,0xadba2c07,0xaa4ea814,0xa5db2b05,0xaaaa2f1a,0xafc92f02,0xafe62f02,0x2993a17e,0x2e3fa765,0xafa02fff,0xa17e2d72,0x2e3facb0,0x2e5eb000,0xad4d2eb5,0x2f91ac5d,0x2fedaf5a,
0xaee92ff8,0xaffc2faf,0xad4d230e,0x244e217e,0x25db2aaa,0xaf6e2fe6,0xaf6e2fc9,0x2c5da993,0x2fe6adba,0xad722e99,0x1cb62c5d,0x2ed0adba,0x2bb7af30,0xa8d52c07,0x2fa0acd8,0x2ff4af91,
0xa9342e3f,0xae5e2f1a,0xaee92b5e,0x2b05a875,0x2dbaa765,0xac5d2d72,0xae992fff,0x2dbaacb0,0x2f80afd4,0xa7652a4e,0x25152a4e,0x2f46ae99,0x217eacd8,0x230e1fd9,0x2fafad4d,0x2ff8afbc,
0x29f1244e,0xa6a12934,0xafd42dfe,0x2d96acd8,0x2fe6ae3f,0x1cb6217e,0xad722fa0,0x2ed0ae3f,0x2d27af80,0x2875a515,0x28752765,0x2fa0af46,0xa934a5db,0x2c07aa4e,0x2fbcadba,0x2ffcafdd,
0x2f1aacb0,0x2bb7aaaa,0xaff42f80,0x2f1aaed0,0x2f30b000,0x2cd8ac5d,0xac072eb5,0x2f91af5a,0x25dbacd8,0x2dbaad4d,0x2a4e1fd9,0x2fddafbc,0xad722875,0x2e7cae1f,0x2fc9ae1f,0x2fffaff4,
0x2fc9afdd,0x2f80af6e,0xaf463000,0x2fe6afdd,0x2bb7ae5e,0x2fa0af91,0xa8d52d4d,0x2ff4afed,0xa934a17e,0x2fbcafaf,0x2c07a30e,0x2ffcaff8,0xaf5a2d72,0x2fd4afc9,0x2fd4ae7c,0x3000afff,
0x9d4d9e16,0xada6ae7d,0x9b769c84,0xabf0accf,0x985299e4,0xa897aa43,0x90b6957f,0xa102a5d8,0x13db0a48,0x242c1aad,0x191b1712,0x296d2783,0x1c201aad,0x2c632b1a,0x1db21ce9,0x2e112d3a,
0xa3f4a491,0xae51af42,0xa199a2c6,0xac70ad60,0x9e7ba06b,0xa922ab00,0x97129c20,0xa199a688,0x19e410b6,0x24aa1b76,0x1fa81d4d,0x2a112833,0x222f2102,0x2ce82bf0,0x2445235d,0x2ec92dd8,
0xa6a1a79c,0xaefcb004,0xa4aaa5a5,0xace8adf2,0xa166a35d,0xa9acabbe,0x99e49edf,0xa22fa738,0x1ce913db,0x25281c20,0x2262206b,0x2ab528a4,0x2528242c,0x2d6d2c63,0x271f2623,0x2f822e77,
0xa8a4a954,0xafa8b067,0xa688a7e8,0xad60ae84,0xa38fa528,0xaa37ac3d,0x9c20a0d0,0xa2c6a7e8,0x1edf157f,0x25a51c84,0x2478222f,0x2b592915,0x273825d8,0x2df22ccf,0x28fc284c,0x301d2f16,
0xa9f8aadb,0xb02ab0ca,0xa833a915,0xadd8af16,0xa4dca6a1,0xaac1ac9c,0x9d4da22f,0xa35da84c,0x206b1712,0x26231ce9,0x25bf23f4,0x2bfd2987,0x28a42783,0x2e772d3a,0x2a692987,0x307a2fb5,
0xab4cac31,0xb081b12e,0xa922aa37,0xae51afa8,0xa5f1a80d,0xab4cacfb,0x9e7ba38f,0xa3f4a8a4,0x21661852,0x26a11d4d,0x270524dc,0x2c5029f8,0x29ac2897,0x2efc2da6,0x2bd72ac1,0x30d7302a,
0xac50acf5,0xb0d7b192,0xaa11ab59,0xaec9b01d,0xa705a8ca,0xabd7ad5a,0x9fa8a478,0xa445a8fc,0x2262191b,0x271f1db2,0x282625bf,0x2ca22a69,0x2ab5296d,0x2f822e11,0x2ca22bfd,0x3135307a,
0xacfbadb9,0xb12eb1f7,0xab00ac3d,0xaf42b067,0xa80da987,0xac31adb9,0xa06ba528,0xa491a954,0x235d19e4,0x279c1e16,0x28ca26a1,0x2cf52adb,0x2bbe2a43,0x30042e7d,0x2d5a2c9c,0x319230ca,
0xb185b25c,0xb426b4cc,0xafbbb0b1,0xb1c6b306,0xac76ae18,0xaea3b08a,0xa4dca9ac,0xa738ac37,0x280d1e7b,0x2a0520d0,0x2d472b4c,0x2fdb2d6d,0x30472ee9,0x32663128,0x31f0311b,0x347933a8,
0xb1ddb2c1,0xb453b501,0xb01ab0fb,0xb204b352,0xacbcae77,0xaee9b0ba,0xa528aa05,0xa783ac63,0x284c1edf,0x2a432102,0x2d992bbe,0x30172da6,0x308a2f55,0x32aa315f,0x324f316b,0x34aa33fc,
0xb235b327,0xb481b537,0xb057b145,0xb242b39e,0xad01aed6,0xaf2fb0eb,0xa573aa5d,0xa7cfac90,0x288b1f44,0x2a822134,0x2deb2c18,0x30412ddf,0x30ce2fc2,0x32ef3196,0x32ae31bc,0x34db3428,
0xb28db38e,0xb4afb56d,0xb094b18f,0xb280b3eb,0xad47af36,0xaf75b11b,0xa5bfaab5,0xa80dacbc,0x28ca1fa8,0x2ac12166,0x2e3e2c50,0x306a2e18,0x31113017,0x333531cd,0x330d320e,0x350d3452,
0xb2e5b3f5,0xb4ddb5a3,0xb0d1b1da,0xb2beb41c,0xad8caf95,0xafbbb14b,0xa60aab0d,0xa833ace8,0x29092006,0x2b002199,0x2e902c89,0x30942e51,0x3155304d,0x337a3204,0x336d325f,0x3540347c,
0xb33eb42e,0xb50cb5da,0xb10eb224,0xb2fcb443,0xadd2aff5,0xb001b17c,0xa655ab65,0xa859ad14,0x29482039,0x2b4021cb,0x2ee32cc2,0x30be2e8a,0x31993084,0x33c0323b,0x33cd32b1,0x357234a6,
0xb398b463,0xb53ab612,0xb14bb26f,0xb33bb469,0xae18b02a,0xb024b1ac,0xa6a1abbe,0xa87ead40,0x2987206b,0x2b7f21fd,0x2f362cfb,0x30e72ec3,0x31dd30ba,0x34033273,0x34173303,0x35a534d1,
0xb3f2b497,0xb569b64a,0xb189b2bb,0xb37ab490,0xae5eb05a,0xb047b1dd,0xa6ecac0b,0xa8a4ad6d,0x29c6209d,0x2bbe222f,0x2f882d34,0x31112efc,0x322130f1,0x342632aa,0x34483356,0x35d934fc,
0xb599b682,0xb722b82e,0xb3b9b4b7,0xb4ddb5f9,0xb06ab20e,0xb185b398,0xa8caad99,0xa9f8aefc,0x2bfd2262,0x2cfb23f4,0x313b2f36,0x328d3081,0x344932e2,0x35693453,0x360d3527,0x37bd368b,
0xb5c9b6bb,0xb755b84d,0xb3f8b4df,0xb4feb622,0xb08db23e,0xb1a9b3ca,0xa8f0adc5,0xaa1eaf29,0x2c1e2294,0x2d1b2413,0x31652f6f,0x32b7309d,0x346d331a,0x358e3470,0x36413553,0x37f536ba,
0xb5f9b6f5,0xb789b86d,0xb41cb506,0xb51fb64c,0xb0b1b26f,0xb1cdb3fc,0xa915adf2,0xaa43af55,0x2c3d22c6,0x2d3a242c,0x318f2fa8,0x32e230ba,0x34903352,0x35b3348d,0x3676357e,0x381736e8,
0xb629b72f,0xb7bdb88d,0xb43cb52e,0xb540b676,0xb0d4b2a1,0xb1f0b417,0xa93bae1e,0xaa69af82,0x2c5d22f9,0x2d5a2445,0x31b92fe2,0x330d30d7,0x34b4338b,0x35d934aa,0x36ab35ab,0x38343717,
0xb65ab76a,0xb7f1b8ad,0xb45cb556,0xb561b6a0,0xb0f7b2d2,0xb214b430,0xa961ae4b,0xaa8fafaf,0x2c7d232b,0x2d79245f,0x31e3300e,0x333830f4,0x34d833c3,0x35fe34c7,0x36e035d7,0x38513746,
0xb68bb7a5,0xb813b8ce,0xb47cb57e,0xb582b6ca,0xb11bb303,0xb238b449,0xa987ae77,0xaab5afdb,0x2c9c235d,0x2d992478,0x320e302a,0x33633111,0x34fc33fc,0x362434e4,0x37173604,0x386f3775,
0xb6bdb7e2,0xb82eb8f0,0xb49cb5a7,0xb5a3b6f5,0xb13eb335,0xb25cb463,0xa9acaea3,0xaadbb004,0x2cbc238f,0x2db92491,0x32383047,0x338e312e,0x3520341a,0x364a3501,0x374d3631,0x388d37a5,
0xb6efb80f,0xb849b911,0xb4bdb5d0,0xb5c5b720,0xb162b366,0xb280b47c,0xa9d2aed0,0xab00b01a,0x2cdb23c2,0x2dd824aa,0x32623064,0x33b9314b,0x35453437,0x3670351f,0x3785365e,0x38ab37d6,
0xb865b934,0xb94dba5c,0xb5e7b74c,0xb6fcb85a,0xb2a4b495,0xb3c6b564,0xab26b031,0xac2bb0e4,0x2df824c3,0x2ef6258c,0x33e43168,0x34a13252,0x3697353c,0x37d4362d,0x38ca3803,0x39d038d0,
0xb880b957,0xb96bba84,0xb609b777,0xb720b872,0xb2c8b4af,0xb3ebb57e,0xab4cb047,0xac3db0fb,0x2e1824dc,0x2f1625a5,0x34083185,0x34b7326f,0x36bd355a,0x37fd364c,0x38e9381c,0x39f338eb,
0xb89cb97a,0xb98abaad,0xb62bb7a4,0xb744b88a,0xb2ecb4c9,0xb408b599,0xab72b05d,0xac50b111,0x2e3724f5,0x2f3625bf,0x341e31a2,0x34ce328d,0x36e43577,0x3813366b,0x39093835,0x3a173906,
0xb8b9b99e,0xb9aabad7,0xb64db7d0,0xb768b8a2,0xb310b4e2,0xb41ab5b3,0xab98b074,0xac63b128,0x2e57250f,0x2f5525d8,0x343331c0,0x34e432aa,0x370b3595,0x3828368a,0x3929384e,0x3a3b3922,
0xb8d6b9c3,0xb9cabb02,0xb670b7fd,0xb78cb8ba,0xb335b4fc,0xb42db5ce,0xabbeb08a,0xac76b13e,0x2e772528,0x2f7525f1,0x344931dd,0x34fa32c8,0x373335b3,0x383d36a9,0x39493868,0x3a60393e,
0xb8f3b9e8,0xb9ebbb2d,0xb693b815,0xb7b1b8d2,0xb359b516,0xb43fb5e9,0xabe3b0a1,0xac89b155,0x2e972541,0x2f95260a,0x345f31fa,0x351132e5,0x375b35d2,0x385236c8,0x396a3881,0x3a86395a,
0xb910ba0e,0xba0cbb59,0xb6b6b82c,0xb7d6b8eb,0xb37db530,0xb452b604,0xac05b0b7,0xac9cb16b,0x2eb6255a,0x2fb52623,0x34753217,0x35273303,0x378335f0,0x386836e8,0x398c389b,0x3aac3977,
0xb92eba35,0xba2dbb87,0xb6d9b843,0xb7fbb904,0xb3a2b54a,0xb464b61e,0xac18b0ce,0xacafb182,0x2ed62573,0x2fd5263c,0x348b3235,0x353e3321,0x37ab360e,0x387d3708,0x39ae38b6,0x3ad33994,
0x9ce99db2,0xad3aae11,0x9aad9c20,0xab1aac63,0x9712991b,0xa783a96d,0x8a4893db,0x9aada42c,0x157f10b6,0x25d82102,0x19e41852,0x2a432897,0x1c841b76,0x2ccf2bf0,0x1e161d4d,0x2e7d2da6,
0xa35da445,0xadd8aec9,0xa102a22f,0xabf0ace8,0x9d4d9fa8,0xa833aa11,0x90b699e4,0x9b76a4aa,0x1c201712,0x26882199,0x206b1e7b,0x2b002922,0x22c62199,0x2d602c70,0x249123f4,0x2f422e51,
0xa623a71f,0xae77af82,0xa42ca528,0xac63ad6d,0xa06ba262,0xa8a4aab5,0x93db9ce9,0x9c20a528,0x1edf19e4,0x2738222f,0x235d2166,0x2bbe29ac,0x25a524aa,0x2df22ce8,0x279c26a1,0x30042efc,
0xa84ca8fc,0xaf16b01d,0xa5d8a738,0xaccfadf2,0xa22fa478,0xa915ab59,0x957f9edf,0x9c84a5a5,0x20d01c20,0x27e822c6,0x2528238f,0x2c3d2a37,0x27e82688,0x2e842d60,0x295428a4,0x30672fa8,
0xa987aa69,0xafb5b07a,0xa783a8a4,0xad3aae77,0xa3f4a5bf,0xa987abfd,0x9712a06b,0x9ce9a623,0x222f1d4d,0x284c235d,0x26a124dc,0x2c9c2ac1,0x29152833,0x2f162dd8,0x2adb29f8,0x30ca302a,
0xaac1abd7,0xb02ab0d7,0xa897a9ac,0xada6aefc,0xa4dca705,0xa9f8ac50,0x9852a166,0x9d4da6a1,0x238f1e7b,0x28a423f4,0x280d25f1,0x2cfb2b4c,0x2a372922,0x2fa82e51,0x2c312b4c,0x312e3081,
0xabfdaca2,0xb07ab135,0xa96daab5,0xae11af82,0xa5bfa826,0xaa69aca2,0x991ba262,0x9db2a71f,0x24781fa8,0x28fc2445,0x28ca2705,0x2d5a2bd7,0x2b592a11,0x301d2ec9,0x2cf52c50,0x319230d7,
0xac9cad5a,0xb0cab192,0xaa43abbe,0xae7db004,0xa6a1a8ca,0xaadbacf5,0x99e4a35d,0x9e16a79c,0x2528206b,0x29542491,0x2987280d,0x2db92c31,0x2c3d2b00,0x30672f42,0x2db92cfb,0x31f7312e,
0xb11bb1f0,0xb3a8b479,0xaee9b047,0xb128b266,0xab4cad47,0xad6dafdb,0x9e7ba80d,0xa0d0aa05,0x29ac24dc,0x2c372738,0x2e182c76,0x308a2ea3,0x30b12fbb,0x330631c6,0x325c3185,0x34cc3426,
0xb16bb24f,0xb3fcb4aa,0xaf55b08a,0xb15fb2aa,0xabbead99,0xada6b017,0x9edfa84c,0xa102aa43,0x2a052528,0x2c632783,0x2e772cbc,0x30ba2ee9,0x30fb301a,0x33523204,0x32c131dd,0x35013453,
0xb1bcb2ae,0xb428b4db,0xafc2b0ce,0xb196b2ef,0xac18adeb,0xaddfb041,0x9f44a88b,0xa134aa82,0x2a5d2573,0x2c9027cf,0x2ed62d01,0x30eb2f2f,0x31453057,0x339e3242,0x33273235,0x35373481,
0xb20eb30d,0xb452b50d,0xb017b111,0xb1cdb335,0xac50ae3e,0xae18b06a,0x9fa8a8ca,0xa166aac1,0x2ab525bf,0x2cbc280d,0x2f362d47,0x311b2f75,0x318f3094,0x33eb3280,0x338e328d,0x356d34af,
0xb25fb36d,0xb47cb540,0xb04db155,0xb204b37a,0xac89ae90,0xae51b094,0xa006a909,0xa199ab00,0x2b0d260a,0x2ce82833,0x2f952d8c,0x314b2fbb,0x31da30d1,0x341c32be,0x33f532e5,0x35a334dd,
0xb2b1b3cd,0xb4a6b572,0xb084b199,0xb23bb3c0,0xacc2aee3,0xae8ab0be,0xa039a948,0xa1cbab40,0x2b652655,0x2d142859,0x2ff52dd2,0x317c3001,0x3224310e,0x344332fc,0x342e333e,0x35da350c,
0xb303b417,0xb4d1b5a5,0xb0bab1dd,0xb273b403,0xacfbaf36,0xaec3b0e7,0xa06ba987,0xa1fdab7f,0x2bbe26a1,0x2d40287e,0x302a2e18,0x31ac3024,0x326f314b,0x3469333b,0x34633398,0x3612353a,
0xb356b448,0xb4fcb5d9,0xb0f1b221,0xb2aab426,0xad34af88,0xaefcb111,0xa09da9c6,0xa22fabbe,0x2c0b26ec,0x2d6d28a4,0x305a2e5e,0x31dd3047,0x32bb3189,0x3490337a,0x349733f2,0x364a3569,
0xb527b60d,0xb68bb7bd,0xb2e2b449,0xb453b569,0xaf36b13b,0xb081b28d,0xa262abfd,0xa3f4acfb,0x2d9928ca,0x2efc29f8,0x320e306a,0x33983185,0x34b733b9,0x35f934dd,0x36823599,0x382e3722,
0xb553b641,0xb6bab7f5,0xb31ab46d,0xb470b58e,0xaf6fb165,0xb09db2b7,0xa294ac1e,0xa413ad1b,0x2dc528f0,0x2f292a1e,0x323e308d,0x33ca31a9,0x34df33f8,0x362234fe,0x36bb35c9,0x384d3755,
0xb57eb676,0xb6e8b817,0xb352b490,0xb48db5b3,0xafa8b18f,0xb0bab2e2,0xa2c6ac3d,0xa42cad3a,0x2df22915,0x2f552a43,0x326f30b1,0x33fc31cd,0x3506341c,0x364c351f,0x36f535f9,0x386d3789,
0xb5abb6ab,0xb717b834,0xb38bb4b4,0xb4aab5d9,0xafe2b1b9,0xb0d7b30d,0xa2f9ac5d,0xa445ad5a,0x2e1e293b,0x2f822a69,0x32a130d4,0x341731f0,0x352e343c,0x36763540,0x372f3629,0x388d37bd,
0xb5d7b6e0,0xb746b851,0xb3c3b4d8,0xb4c7b5fe,0xb00eb1e3,0xb0f4b338,0xa32bac7d,0xa45fad79,0x2e4b2961,0x2faf2a8f,0x32d230f7,0x34303214,0x3556345c,0x36a03561,0x376a365a,0x38ad37f1,
0xb604b717,0xb775b86f,0xb3fcb4fc,0xb4e4b624,0xb02ab20e,0xb111b363,0xa35dac9c,0xa478ad99,0x2e772987,0x2fdb2ab5,0x3303311b,0x34493238,0x357e347c,0x36ca3582,0x37a5368b,0x38ce3813,
0xb631b74d,0xb7a5b88d,0xb41ab520,0xb501b64a,0xb047b238,0xb12eb38e,0xa38facbc,0xa491adb9,0x2ea329ac,0x30042adb,0x3335313e,0x3463325c,0x35a7349c,0x36f535a3,0x37e236bd,0x38f0382e,
0xb65eb785,0xb7d6b8ab,0xb437b545,0xb51fb670,0xb064b262,0xb14bb3b9,0xa3c2acdb,0xa4aaadd8,0x2ed029d2,0x301a2b00,0x33663162,0x347c3280,0x35d034bd,0x372035c5,0x380f36ef,0x39113849,
0xb803b8ca,0xb8d0b9d0,0xb53cb697,0xb62db7d4,0xb168b3e4,0xb252b4a1,0xa4c3adf8,0xa58caef6,0x30312b26,0x30e42c2b,0x349532a4,0x356433c6,0x374c35e7,0x385a36fc,0x39343865,0x3a5c394d,
0xb81cb8e9,0xb8ebb9f3,0xb55ab6bd,0xb64cb7fd,0xb185b408,0xb26fb4b7,0xa4dcae18,0xa5a5af16,0x30472b4c,0x30fb2c3d,0x34af32c8,0x357e33eb,0x37773609,0x38723720,0x39573880,0x3a84396b,
0xb835b909,0xb906ba17,0xb577b6e4,0xb66bb813,0xb1a2b41e,0xb28db4ce,0xa4f5ae37,0xa5bfaf36,0x305d2b72,0x31112c50,0x34c932ec,0x35993408,0x37a4362b,0x388a3744,0x397a389c,0x3aad398a,
0xb84eb929,0xb922ba3b,0xb595b70b,0xb68ab828,0xb1c0b433,0xb2aab4e4,0xa50fae57,0xa5d8af55,0x30742b98,0x31282c63,0x34e23310,0x35b3341a,0x37d0364d,0x38a23768,0x399e38b9,0x3ad739aa,
0xb868b949,0xb93eba60,0xb5b3b733,0xb6a9b83d,0xb1ddb449,0xb2c8b4fa,0xa528ae77,0xa5f1af75,0x308a2bbe,0x313e2c76,0x34fc3335,0x35ce342d,0x37fd3670,0x38ba378c,0x39c338d6,0x3b0239ca,
0xb881b96a,0xb95aba86,0xb5d2b75b,0xb6c8b852,0xb1fab45f,0xb2e5b511,0xa541ae97,0xa60aaf95,0x30a12be3,0x31552c89,0x35163359,0x35e9343f,0x38153693,0x38d237b1,0x39e838f3,0x3b2d39eb,
0xb89bb98c,0xb977baac,0xb5f0b783,0xb6e8b868,0xb217b475,0xb303b527,0xa55aaeb6,0xa623afb5,0x30b72c05,0x316b2c9c,0x3530337d,0x36043452,0x382c36b6,0x38eb37d6,0x3a0e3910,0x3b593a0c,
0xb8b6b9ae,0xb994bad3,0xb60eb7ab,0xb708b87d,0xb235b48b,0xb321b53e,0xa573aed6,0xa63cafd5,0x30ce2c18,0x31822caf,0x354a33a2,0x361e3464,0x384336d9,0x390437fb,0x3a35392e,0x3b873a2d,
0x214d2216,0x319b326c,0x1f762084,0x2fe830c8,0x1c521de4,0x2c962e40,0x14b6197f,0x250229d7,0x97db8e48,0xa82c9ead,0x9d1b9b12,0xad6bab82,0xa0209ead,0xb05eaf14,0xa1b2a0e9,0xb204b131,
0x27f32890,0x3241332b,0x259826c6,0x306a3156,0x227b246b,0x2d202efb,0x1b122020,0x25982a87,0x9de494b6,0xa8aa9f76,0xa3a8a14d,0xae0eac32,0xa62fa502,0xb0e1afe8,0xa845a75d,0xb2b6b1cc,
0x2aa02b9b,0x32e733e8,0x28aa29a5,0x30e131e5,0x2566275d,0x2daa2fb6,0x1de422df,0x262f2b36,0xa0e997db,0xa927a020,0xa661a46b,0xaeb0aca2,0xa927a82c,0xb163b05e,0xab1daa22,0xb368b266,
0x2ca22d52,0x338d3452,0x2a872be6,0x31563273,0x278f2927,0x2e333039,0x202024cf,0x26c62be6,0xa2df997f,0xa9a5a084,0xa877a62f,0xaf53ad13,0xab36a9d7,0xb1e5b0c8,0xacfaac4b,0xb40cb300,
0x2df52ed6,0x341834b0,0x2c322d13,0x31cc3300,0x28dc2aa0,0x2ebd3096,0x214d262f,0x275d2c4b,0xa46b9b12,0xaa22a0e9,0xa9bea7f3,0xaff5ad84,0xaca2ab82,0xb266b131,0xae65ad84,0xb464b399,
0x2f46302c,0x346a350c,0x2d202e33,0x3241338d,0x29f02c0c,0x2f4630f3,0x227b278f,0x27f32ca2,0xa5669c52,0xaaa0a14d,0xab04a8dc,0xb04badf5,0xadaaac96,0xb2e7b19b,0xafcfaebd,0xb4bcb418,
0x304b30ed,0x34bc3568,0x2e0e2f53,0x32b6340c,0x2b042cc8,0x2fcf3150,0x23a82877,0x28452cfa,0xa6619d1b,0xab1da1b2,0xac25a9be,0xb09cae65,0xaeb0ad6b,0xb368b204,0xb09caff5,0xb512b464,
0x30f331ad,0x350c35c4,0x2efb3039,0x332b3452,0x2c0c2d84,0x302c31ad,0x246b2927,0x28902d52,0xa75d9de4,0xab9ba216,0xacc8aaa0,0xb0edaed6,0xafb6ae40,0xb3e8b26c,0xb150b096,0xb568b4b0,
0x355d361e,0x37c63867,0x339f3497,0x359836b4,0x3071320a,0x32913473,0x28dc2daa,0x2b363032,0xac0ca27b,0xae01a4cf,0xb13eaf46,0xb3bdb163,0xb434b2d5,0xb627b506,0xb5beb4fa,0xb826b73e,
0x35ac3678,0x3808388f,0x340934dd,0x35cf36f5,0x30b53266,0x32d534a0,0x29272e01,0x2b82305e,0xac4ba2df,0xae40a502,0xb18eafb6,0xb406b19b,0xb473b33d,0xb663b539,0xb612b545,0xb84cb784,
0x35fb36d0,0x382c38b7,0x34433521,0x36073736,0x30f932c2,0x331834ce,0x29722e59,0x2bcd308a,0xac89a344,0xae7ea534,0xb1dfb013,0xb42eb1d2,0xb4b3b3a5,0xb6a0b56b,0xb666b58f,0xb872b7c9,
0x36493728,0x385038de,0x347c3565,0x363e3776,0x313e331e,0x335c34fa,0x29be2eb0,0x2c0c30b5,0xacc8a3a8,0xaebda566,0xb22fb04b,0xb455b20a,0xb4f1b406,0xb6dcb59d,0xb6b9b5d8,0xb898b807,
0x3697377e,0x38743904,0x34b635a9,0x367537b6,0x3182337a,0x339f3527,0x2a092f08,0x2c3230e1,0xad07a406,0xaefba598,0xb27fb083,0xb47cb241,0xb530b43a,0xb717b5cf,0xb70cb621,0xb8bdb828,
0x36e437d4,0x3897392a,0x34ee35ed,0x36ab37f5,0x31c633d6,0x33e23554,0x2a542f5f,0x2c57310c,0xad45a439,0xaf3aa5cb,0xb2cfb0bb,0xb4a4b279,0xb56eb46d,0xb752b601,0xb75db669,0xb8e1b84a,
0x37303814,0x38b9394e,0x3527362f,0x36e1381a,0x320a3418,0x34123580,0x2aa02fb6,0x2c7d3137,0xad84a46b,0xaf78a5fd,0xb31eb0f3,0xb4cbb2b0,0xb5acb4a0,0xb78cb632,0xb7adb6b1,0xb905b86b,
0x377c383e,0x38db3972,0x355f3672,0x37173838,0x324e3446,0x343435ac,0x2aeb3007,0x2ca23163,0xadc3a49d,0xafb6a62f,0xb36eb12b,0xb4f1b2e7,0xb5eab4d4,0xb7c6b663,0xb7fdb6f8,0xb928b88b,
0x38fd3996,0x39f33a91,0x374c3857,0x3874393e,0x345535d8,0x355d3730,0x2cc8318e,0x2df532e7,0xaff5a661,0xb0f3a7f3,0xb518b31e,0xb649b46a,0xb800b694,0xb8dbb808,0xb94bb8ab,0xba45b99b,
0x391e39b8,0x3a0f3aad,0x37813875,0x388c3959,0x34763604,0x357d375a,0x2cee31b9,0x2e1a3312,0xb01aa694,0xb112a813,0xb53fb356,0xb66fb485,0xb81cb6c5,0xb8f5b81f,0xb96db8cb,0xba61b9b7,
0x393e39da,0x3a2b3ac7,0x37b63893,0x38a53974,0x3497362f,0x359d3784,0x2d1331e5,0x2e40333d,0xb039a6c6,0xb131a82c,0xb565b38d,0xb694b4a0,0xb838b6f5,0xb90fb836,0xb98eb8ea,0xba7cb9d2,
0x395e39fb,0x3a453ae0,0x37ea38b0,0x38bd398e,0x34b9365b,0x35be37ad,0x2d393210,0x2e653368,0xb058a6f8,0xb150a845,0xb58cb3c3,0xb6b9b4bc,0xb854b725,0xb928b84c,0xb9aeb909,0xba97b9ed,
0x397d3a1b,0x3a5f3af9,0x380f38cd,0x38d539a8,0x34da3686,0x35de37d7,0x2d5e323b,0x2e8b3393,0xb077a72a,0xb16fa85e,0xb5b2b3fa,0xb6deb4d7,0xb870b755,0xb941b863,0xb9ceb927,0xbab0ba07,
0x399b3a3a,0x3a793b10,0x382838ea,0x38ed39c1,0x34fa36b1,0x35fe3800,0x2d843266,0x2eb033bd,0xb096a75d,0xb18ea877,0xb5d8b418,0xb703b4f1,0xb88bb784,0xb95ab879,0xb9edb945,0xbac9ba21,
0x39b93a58,0x3a913b26,0x38423906,0x390439da,0x351b36dc,0x361e3814,0x2daa3291,0x2ed633e8,0xb0b5a78f,0xb1ada890,0xb5feb434,0xb728b50c,0xb8a6b7b3,0xb972b88f,0xba0bb962,0xbae0ba3a,
0x39d73a75,0x3aa93b3c,0x385b3922,0x391b39f2,0x353c3706,0x363e3828,0x2dcf32bc,0x2efb3409,0xb0d4a7c1,0xb1cca8aa,0xb624b44f,0xb74cb527,0xb8c1b7e2,0xb98ab8a5,0xba29b97f,0xbaf7ba52,
0x3ac03b50,0x3b5e3bcb,0x39323a0a,0x39de3ab8,0x365e383c,0x375738d7,0x2f21341f,0x302634c8,0xb1eba8c3,0xb2e1a98c,0xb770b542,0xb846b615,0xb9a2b8bb,0xba51b960,0xbb0dba6a,0xbb9cbb11,
0x3ad73b63,0x3b6e3bd6,0x39493a22,0x39f23acb,0x367d3850,0x377638ea,0x2f463434,0x303934dd,0xb20aa8dc,0xb300a9a5,0xb795b55d,0xb857b62f,0xb9b9b8d0,0xba65b974,0xbb22ba81,0xbba9bb24,
0x3aec3b75,0x3b7d3bdf,0x395f3a39,0x3a063ade,0x369d3864,0x379538fd,0x2f6c3449,0x304b34f1,0xb229a8f5,0xb31ea9be,0xb7b8b577,0xb868b649,0xb9d0b8e5,0xba79b987,0xbb36ba97,0xbbb6bb35,
0x3b013b86,0x3b8c3be7,0x39753a4f,0x3a193af0,0x36bc3878,0x37b3390f,0x2f91345e,0x305e3506,0xb247a90e,0xb33da9d7,0xb7dcb592,0xb879b663,0xb9e7b8fa,0xba8cb99a,0xbb4abaad,0xbbc2bb46,
0x3b153b96,0x3b993bee,0x398a3a65,0x3a2d3b02,0x36dc388b,0x37d13921,0x2fb63473,0x3071351b,0xb266a927,0xb35ca9f0,0xb800b5ac,0xb88ab67d,0xb9fdb90f,0xba9fb9ad,0xbb5cbac3,0xbbccbb56,
0x3b283ba5,0x3ba63bf4,0x39a03a7a,0x3a3f3b13,0x36fb389e,0x37ef3933,0x2fdc3488,0x30833530,0xb285a940,0xb37aaa09,0xb811b5c7,0xb89bb697,0xba12b924,0xbab1b9c0,0xbb6dbad7,0xbbd6bb65,
0x3b3b3bb3,0x3bb23bf9,0x39b53a8f,0x3a523b24,0x371a38b2,0x38073945,0x3001349d,0x30963545,0xb2a4a959,0xb399aa22,0xb823b5e1,0xb8abb6b1,0xba28b938,0xbac3b9d2,0xbb7ebaeb,0xbbdfbb74,
0x3b4d3bc0,0x3bbd3bfc,0x39ca3aa4,0x3a643b34,0x373938c5,0x38153957,0x301334b3,0x30a9355a,0xb2c2a972,0xb3b7aa3b,0xb834b5fb,0xb8bcb6ca,0xba3cb94c,0xbad4b9e4,0xbb8dbaff,0xbbe6bb82,
0x20e921b2,0x31313204,0x1ead2020,0x2f14305e,0x1b121d1b,0x2b822d6b,0xe4817db,0x1ead282c,0x997f94b6,0xa9d7a502,0x9de49c52,0xae40ac96,0xa0849f76,0xb0c8afe8,0xa216a14d,0xb26cb19b,
0x275d2845,0x31cc32b6,0x2502262f,0x2fe830e1,0x214d23a8,0x2c322e0e,0x14b61de4,0x1f7628aa,0xa0209b12,0xaa87a598,0xa46ba27b,0xaefbad20,0xa6c6a598,0xb156b06a,0xa890a7f3,0xb32bb241,
0x2a222b1d,0x32663368,0x282c2927,0x305e3163,0x246b2661,0x2ca22eb0,0x17db20e9,0x20202927,0xa2df9de4,0xab36a62f,0xa75da566,0xafb6adaa,0xa9a5a8aa,0xb1e5b0e1,0xab9baaa0,0xb3e8b2e7,
0x2c4b2cfa,0x3300340c,0x29d72b36,0x30c831e5,0x262f2877,0x2d132f53,0x197f22df,0x208429a5,0xa4cfa020,0xabe6a6c6,0xa927a78f,0xb039ae33,0xabe6aa87,0xb273b156,0xad52aca2,0xb452b38d,
0x2d842e65,0x33993464,0x2b822ca2,0x31313266,0x27f329be,0x2d842ff5,0x1b12246b,0x20e92a22,0xa62fa14d,0xac4ba75d,0xaaa0a8dc,0xb096aebd,0xad13ac32,0xb300b1cc,0xaed6adf5,0xb4b0b418,
0x2ebd2fcf,0x341834bc,0x2c962daa,0x319b32e7,0x28dc2b04,0x2df5304b,0x1c522566,0x214d2aa0,0xa78fa27b,0xaca2a7f3,0xac0ca9f0,0xb0f3af46,0xae33ad20,0xb38db241,0xb02caf46,0xb50cb46a,
0x2ff5309c,0x34643512,0x2d6b2eb0,0x32043368,0x29be2c25,0x2e65309c,0x1d1b2661,0x21b22b1d,0xa877a3a8,0xacfaa845,0xacc8ab04,0xb150afcf,0xaf53ae0e,0xb40cb2b6,0xb0edb04b,0xb568b4bc,
0x30963150,0x34b03568,0x2e402fb6,0x326c33e8,0x2aa02cc8,0x2ed630ed,0x1de4275d,0x22162b9b,0xa927a46b,0xad52a890,0xad84ac0c,0xb1adb02c,0xb039aefb,0xb452b32b,0xb1adb0f3,0xb5c4b50c,
0x34fa35be,0x373e3826,0x32d53434,0x35063627,0x2f46313e,0x316333bd,0x227b2c0c,0x24cf2e01,0xadaaa8dc,0xb032ab36,0xb20ab071,0xb473b291,0xb497b39f,0xb6b4b598,0xb61eb55d,0xb867b7c6,
0x35453612,0x3784384c,0x333d3473,0x35393663,0x2fb6318e,0x319b3406,0x22df2c4b,0x25022e40,0xae01a927,0xb05eab82,0xb266b0b5,0xb4a0b2d5,0xb4ddb409,0xb6f5b5cf,0xb678b5ac,0xb88fb808,
0x358f3666,0x37c93872,0x33a534b3,0x356b36a0,0x301331df,0x31d2342e,0x23442c89,0x25342e7e,0xae59a972,0xb08aabcd,0xb2c2b0f9,0xb4ceb318,0xb521b443,0xb736b607,0xb6d0b5fb,0xb8b7b82c,
0x35d836b9,0x38073898,0x340634f1,0x359d36dc,0x304b322f,0x320a3455,0x23a82cc8,0x25662ebd,0xaeb0a9be,0xb0b5ac0c,0xb31eb13e,0xb4fab35c,0xb565b47c,0xb776b63e,0xb728b649,0xb8deb850,
0x3621370c,0x382838bd,0x343a3530,0x35cf3717,0x3083327f,0x3241347c,0x24062d07,0x25982efb,0xaf08aa09,0xb0e1ac32,0xb37ab182,0xb527b39f,0xb5a9b4b6,0xb7b6b675,0xb77eb697,0xb904b874,
0x3669375d,0x384a38e1,0x346d356e,0x36013752,0x30bb32cf,0x327934a4,0x24392d45,0x25cb2f3a,0xaf5faa54,0xb10cac57,0xb3d6b1c6,0xb554b3e2,0xb5edb4ee,0xb7f5b6ab,0xb7d4b6e4,0xb92ab897,
0x36b137ad,0x386b3905,0x34a035ac,0x3632378c,0x30f3331e,0x32b034cb,0x246b2d84,0x25fd2f78,0xafb6aaa0,0xb137ac7d,0xb418b20a,0xb580b412,0xb62fb527,0xb81ab6e1,0xb814b730,0xb94eb8b9,
0x36f837fd,0x388b3928,0x34d435ea,0x366337c6,0x312b336e,0x32e734f1,0x249d2dc3,0x262f2fb6,0xb007aaeb,0xb163aca2,0xb446b24e,0xb5acb434,0xb672b55f,0xb838b717,0xb83eb77c,0xb972b8db,
0x38ab394b,0x399b3a45,0x36943800,0x380838db,0x331e3518,0x346a3649,0x26612ff5,0x27f330f3,0xb18eacc8,0xb2e7adf5,0xb5d8b455,0xb730b55d,0xb857b74c,0xb93eb874,0xb996b8fd,0xba91b9f3,
0x38cb396d,0x39b73a61,0x36c5381c,0x381f38f5,0x3356353f,0x3485366f,0x2694301a,0x28133112,0xb1b9acee,0xb312ae1a,0xb604b476,0xb75ab57d,0xb875b781,0xb959b88c,0xb9b8b91e,0xbaadba0f,
0x38ea398e,0x39d23a7c,0x36f53838,0x3836390f,0x338d3565,0x34a03694,0x26c63039,0x282c3131,0xb1e5ad13,0xb33dae40,0xb62fb497,0xb784b59d,0xb893b7b6,0xb974b8a5,0xb9dab93e,0xbac7ba2b,
0x390939ae,0x39ed3a97,0x37253854,0x384c3928,0x33c3358c,0x34bc36b9,0x26f83058,0x28453150,0xb210ad39,0xb368ae65,0xb65bb4b9,0xb7adb5be,0xb8b0b7ea,0xb98eb8bd,0xb9fbb95e,0xbae0ba45,
0x392739ce,0x3a073ab0,0x37553870,0x38633941,0x33fa35b2,0x34d736de,0x272a3077,0x285e316f,0xb23bad5e,0xb393ae8b,0xb686b4da,0xb7d7b5de,0xb8cdb80f,0xb9a8b8d5,0xba1bb97d,0xbaf9ba5f,
0x394539ed,0x3a213ac9,0x3784388b,0x3879395a,0x341835d8,0x34f13703,0x275d3096,0x2877318e,0xb266ad84,0xb3bdaeb0,0xb6b1b4fa,0xb800b5fe,0xb8eab828,0xb9c1b8ed,0xba3ab99b,0xbb10ba79,
0x39623a0b,0x3a3a3ae0,0x37b338a6,0x388f3972,0x343435fe,0x350c3728,0x278f30b5,0x289031ad,0xb291adaa,0xb3e8aed6,0xb6dcb51b,0xb814b61e,0xb906b842,0xb9dab904,0xba58b9b9,0xbb26ba91,
0x397f3a29,0x3a523af7,0x37e238c1,0x38a5398a,0x344f3624,0x3527374c,0x27c130d4,0x28aa31cc,0xb2bcadcf,0xb409aefb,0xb706b53c,0xb828b63e,0xb922b85b,0xb9f2b91b,0xba75b9d7,0xbb3cbaa9,
0x3a6a3b0d,0x3b113b9c,0x38bb39a2,0x39603a51,0x35423770,0x36153846,0x28c331eb,0x298c32e1,0xb41faf21,0xb4c8b026,0xb83cb65e,0xb8d7b757,0xba0ab932,0xbab8b9de,0xbb50bac0,0xbbcbbb5e,
0x3a813b22,0x3b243ba9,0x38d039b9,0x39743a65,0x355d3795,0x362f3857,0x28dc320a,0x29a53300,0xb434af46,0xb4ddb039,0xb850b67d,0xb8eab776,0xba22b949,0xbacbb9f2,0xbb63bad7,0xbbd6bb6e,
0x3a973b36,0x3b353bb6,0x38e539d0,0x39873a79,0x357737b8,0x36493868,0x28f53229,0x29be331e,0xb449af6c,0xb4f1b04b,0xb864b69d,0xb8fdb795,0xba39b95f,0xbadeba06,0xbb75baec,0xbbdfbb7d,
0x3aad3b4a,0x3b463bc2,0x38fa39e7,0x399a3a8c,0x359237dc,0x36633879,0x290e3247,0x29d7333d,0xb45eaf91,0xb506b05e,0xb878b6bc,0xb90fb7b3,0xba4fb975,0xbaf0ba19,0xbb86bb01,0xbbe7bb8c,
0x3ac33b5c,0x3b563bcc,0x390f39fd,0x39ad3a9f,0x35ac3800,0x367d388a,0x29273266,0x29f0335c,0xb473afb6,0xb51bb071,0xb88bb6dc,0xb921b7d1,0xba65b98a,0xbb02ba2d,0xbb96bb15,0xbbeebb99,
0x3ad73b6d,0x3b653bd6,0x39243a12,0x39c03ab1,0x35c73811,0x3697389b,0x29403285,0x2a09337a,0xb488afdc,0xb530b083,0xb89eb6fb,0xb933b7ef,0xba7ab9a0,0xbb13ba3f,0xbba5bb28,0xbbf4bba6,
0x3aeb3b7e,0x3b743bdf,0x39383a28,0x39d23ac3,0x35e13823,0x36b138ab,0x295932a4,0x2a223399,0xb49db001,0xb545b096,0xb8b2b71a,0xb945b807,0xba8fb9b5,0xbb24ba52,0xbbb3bb3b,0xbbf9bbb2,
0x3aff3b8d,0x3b823be6,0x394c3a3c,0x39e43ad4,0x35fb3834,0x36ca38bc,0x297232c2,0x2a3b33b7,0xb4b3b013,0xb55ab0a9,0xb8c5b739,0xb957b815,0xbaa4b9ca,0xbb34ba64,0xbbc0bb4d,0xbbfcbbbd,
0x39b839ba,0x3a973ab5,0x39b339b5,0x3a583a78,0x39af39b1,0x3a153a37,0x39aa39ad,0x39cd39f2,0x39a639a8,0x398239a8,0x39a139a4,0x3933395b,0x399d399f,0x38e03909,0x3999399b,0x388938b5,
0xb979b972,0xb865b832,0xb986b980,0xb8c7b896,0xb994b98d,0xb924b8f6,0xb9a1b99b,0xb97db951,0xb9afb9a8,0xb9d2b9a8,0xb9bcb9b5,0xba21b9fa,0xb9c9b9c3,0xba6bba47,0xb9d6b9d0,0xbab0ba8e,
0xb9f4b9fe,0xbac7bae9,0xb9dfb9e9,0xba7ebaa3,0xb9c9b9d4,0xba2dba56,0xb9b3b9be,0xb9d6ba02,0xb99db9a8,0xb979b9a8,0xb986b992,0xb916b948,0xb970b97b,0xb8adb8e2,0xb958b964,0xb840b877,
0x39373927,0x381a37b7,0x39583948,0x38943858,0x39793969,0x390738ce,0x39993989,0x3974393e,0x39b839a8,0x39da39a8,0x39d639c7,0x3a393a0b,0x39f439e5,0x3a903a65,0x3a113a02,0x3ade3ab8,
0x3a2d3a3f,0x3af43b1a,0x3a093a1b,0x3aa23acc,0x39e339f6,0x3a453a74,0x39bc39d0,0x39df3a13,0x399439a8,0x397039a8,0x396b3980,0x38f83935,0x39413956,0x387a38ba,0x3916392b,0x37e83838,
0xb8f3b8d8,0xb79bb705,0xb929b90e,0xb85fb817,0xb95db943,0xb8eab8a6,0xb990b976,0xb96bb92b,0xb9c0b9a8,0xb9e3b9a8,0xb9f0b9d8,0xba50ba1b,0xba1dba07,0xbab3ba83,0xba49ba33,0xbb0abae0,
0xba64ba7c,0xbb1ebb46,0xba31ba4b,0xbac4baf3,0xb9fcba17,0xba5cba92,0xb9c5b9e1,0xb9e7ba23,0xb98bb9a8,0xb966b9a8,0xb94fb96d,0xb8dbb922,0xb911b930,0xb845b891,0xb8d1b8f1,0xb74eb7ee,
0x38ad3887,0x36ff364e,0x38f838d3,0x382a37ac,0x3941391d,0x38cc387c,0x39863964,0x39623918,0x39c939a8,0x39eb39a8,0x3a0939e9,0x3a673a2b,0x3a453a27,0x3ad53aa0,0x3a7e3a62,0x3b323b05,
0x3b453b6e,0x3bbc3bdd,0x3ae53b17,0x3b573b8f,0x3a733aae,0x3ac73b14,0x39f03a33,0x3a113a71,0x395d39a8,0x393739a8,0x38bc390e,0x384038bf,0x380f3867,0x365f3775,0x36af376a,0x341a3540,
0xb65fb593,0xb389b115,0xb7e8b726,0xb625b4f9,0xb8adb852,0xb830b748,0xb958b905,0xb933b8b5,0xb9f4b9a8,0xba15b9a8,0xba7eba3b,0xbad1ba78,0xbaf4babc,0xbb63bb20,0xbb57bb28,0xbbc6bb9b,
0xbb68bb91,0xbbd0bbed,0xbb04bb39,0xbb6fbba6,0xba89bac9,0xbadbbb2b,0xb9f8ba43,0xba19ba7f,0xb954b9a8,0xb92eb9a8,0xb89eb8fb,0xb820b8ab,0xb7b2b83d,0xb5ebb71b,0xb60eb6e3,0xb2deb4b1,
0x35bc34d5,0x32322f0e,0x377a369e,0x35b13469,0x388e3828,0x380f36ee,0x394f38f1,0x392938a0,0x39fc39a8,0x3a1d39a8,0x3a933a4b,0x3ae53a87,0x3b133ad6,0x3b7a3b36,0x3b783b49,0x3bd93bb1,
0x3b873baf,0x3be13bf8,0x3b213b58,0x3b853bbb,0x3a9e3ae3,0x3aee3b41,0x3a003a52,0x3a213a8e,0x394a39a8,0x392439a8,0x387f38e7,0x37fe3896,0x37423812,0x357636c1,0x356a3659,0x31853420,
0xb517b414,0xb0d7abd9,0xb70ab614,0xb53ab3ae,0xb86fb7f9,0xb7ddb693,0xb946b8dd,0xb91fb88c,0xba04b9a8,0xba25b9a8,0xbaa9ba5a,0xbaf7ba95,0xbb2fbaf0,0xbb90bb4b,0xbb96bb67,0xbbe8bbc4,
0xbba3bbc9,0xbbefbbff,0xbb3dbb74,0xbb9abbcd,0xbab3bafc,0xbb01bb55,0xba09ba62,0xba29ba9c,0xb941b9a8,0xb91bb9a8,0xb85fb8d3,0xb7bdb881,0xb6d2b7cd,0xb4ffb665,0xb4c3b5ce,0xb029b31b,
0x346f32a1,0x2ef52248,0x36993587,0x34c33288,0x385037a1,0x379b3637,0x393c38c9,0x39163877,0x3a0d39a8,0x3a2d39a8,0x3abd3a69,0x3b0a3aa3,0x3b4a3b08,0x3ba33b5f,0x3bb03b82,0x3bf43bd5,
0x3bf83c00,0x3bf93bd4,0x3bac3bdc,0x3be43bfe,0x3b133b69,0x3b543bab,0x3a313aaa,0x3a503ae0,0x391139a8,0x38ea39a8,0x377a386d,0x366b3817,0x34873608,0x313b348d,0x2d9731f4,0xad65291b,
0xac3828b6,0x2ec33365,0xb44bb160,0xb0bea57f,0xb759b5da,0xb648b45d,0xb90cb862,0xb8e5b80d,0xba35b9a8,0xba54b9a8,0xbb1bbab1,0xbb5cbae6,0xbbb5bb72,0xbbe9bbb2,0xbbfcbbe3,0xbbf5bc00,
0xbbfebbfc,0xbbefbbbc,0xbbbdbbe9,0xbbeebc00,0xbb24bb7b,0xbb63bbb9,0xba39bab8,0xba58baed,0xb907b9a8,0xb8e0b9a8,0xb737b858,0xb625b802,0xb40eb5ab,0xb042b42c,0xa9b1b0cb,0x30109a48,
0x25e4ad7e,0xb0beb475,0x33a23036,0x2f8ba3db,0x3715357c,0x360233f7,0x3902384d,0x38db37ee,0x3a3d39a8,0x3a5c39a8,0x3b2c3abf,0x3b6a3af3,0x3bc53b84,0x3bf23bc0,0x3bff3bee,0x3be93c00,
0x3c003bf4,0x3be23ba0,0x3bcc3bf3,0x3bf53bff,0x3b353b8c,0x3b713bc6,0x3a413ac6,0x3a603af9,0x38fd39a8,0x38d639a8,0x36f43842,0x35df37d8,0x3328354c,0x2e913396,0x16482f40,0xb16ca852,
0x251b304e,0x32193534,0xb2adae14,0xad972aac,0xb6d2b51d,0xb5bcb334,0xb8f8b838,0xb8d1b7c2,0xba45b9a8,0xba64b9a8,0xbb3dbacc,0xbb78baff,0xbbd3bb95,0xbbf8bbcb,0xbc00bbf7,0xbbdabbfd,
0xbbfebbe6,0xbbd2bb80,0xbbd9bbfa,0xbbfbbbfb,0xbb45bb9d,0xbb7fbbd1,0xba49bad3,0xba67bb05,0xb8f3b9a8,0xb8ccb9a8,0xb6afb82d,0xb599b7ac,0xb232b4ed,0xac9cb2d2,0x294dace7,0x32c62c83,
0xac06b1db,0xb371b5f1,0x31b62b75,0x2b43adb0,0x368d34bd,0x3576326f,0x38ee3822,0x38c73796,0x3a4d39a8,0x3a6b39a8,0x3b4c3ad9,0x3b853b0b,0x3bdf3ba4,0x3bfd3bd6,0x3bfc3bfd,0x3bc83bf8,
0x3bbd3b5a,0x3b473a99,0x3bfe3bf4,0x3bf93bbe,0x3b8b3bdb,0x3bb83bf7,0x3a6f3b11,0x3a8c3b3e,0x38c139a8,0x389939a8,0x35523780,0x343236cc,0x294d320d,0xad332de2,0xb40eaedc,0xb6a4b408,
0x346336aa,0x36f438b0,0xa6ad3004,0x2e2d3451,0xb52fb1aa,0xb40ead1a,0xb8bcb76a,0xb894b6b5,0xba73b9a8,0xba90b9a8,0xbb92bb17,0xbbbdbb43,0xbbffbbe0,0xbbf6bbf9,0xbbb2bbf0,0xbb35bbb4,
0xbba5bb30,0xbb21ba5e,0xbc00bbeb,0xbbf3bbaa,0xbb98bbe4,0xbbc2bbfb,0xba76bb1d,0xba93bb49,0xb8b7b9a8,0xb88eb9a8,0xb50bb753,0xb3d3b69e,0xa17fb147,0x2f27ac51,0x34b73099,0x37423499,
0xb50bb75e,0xb790b900,0x9cb6b12e,0xb010b4e1,0x34e730e4,0x33892b11,0x38b2373d,0x38893687,0x3a7a39a8,0x3a9739a8,0x3b9e3b22,0x3bc63b4e,0x3c003be8,0x3bef3bfd,0x3b983be5,0x3b0d3b9e,
0x3b893b02,0x3af73a1f,0x3c003bdf,0x3beb3b93,0x3ba33bec,0x3bcb3bfe,0x3a7e3b28,0x3a9b3b53,0x38ad39a8,0x388439a8,0x34c33726,0x33403670,0xa51b3080,0xb08d297f,0xb55eb1c3,0xb7ddb529,
0x35b13807,0x3815394d,0x28843257,0x31093570,0xb49fb01d,0xb2f7a7da,0xb8a8b710,0xb87fb659,0xba81b9a8,0xba9eb9a8,0xbba9bb2e,0xbbcfbb58,0xbbffbbef,0xbbe6bbff,0xbb7abbd7,0xbae1bb86,
0xbb6abad0,0xbacbb9dc,0xbbfdbbd0,0xbbe1bb79,0xbbaebbf2,0xbbd3bc00,0xba85bb33,0xbaa2bb5d,0xb8a3b9a8,0xb87ab9a8,0xb47bb6f9,0xb2adb642,0x2a7aaf72,0x3185a4b6,0x360232ea,0x383a35b6,
0xb654b85d,0xb85fb996,0xac38b37d,0xb201b5fd,0x34572eaa,0x32631e48,0x389e36e3,0x3874362b,0x3a8939a8,0x3aa539a8,0x3bb33b39,0x3bd73b62,0x3bfc3bf5,0x3bdc3c00,0x3b593bc7,0x3ab33b6b,
0x39b739b9,0x3a883aa6,0x39b239b4,0x3a483a68,0x39ae39b0,0x3a033a26,0x39a939ab,0x39bb39e0,0x39a539a7,0x396e3995,0x39a039a3,0x391e3947,0x399c399e,0x38ca38f5,0x3997399a,0x3873389f,
0xb97cb975,0xb87eb84c,0xb98ab983,0xb8deb8ae,0xb997b991,0xb93bb90d,0xb9a5b99e,0xb993b967,0xb9b2b9ab,0xb9e6b9bd,0xb9bfb9b9,0xba34ba0e,0xb9ccb9c6,0xba7dba59,0xb9d9b9d3,0xbac0ba9f,
0xb9efb9f9,0xbab6bad9,0xb9d9b9e4,0xba6aba91,0xb9c4b9cf,0xba18ba42,0xb9aeb9b9,0xb9bfb9ec,0xb997b9a3,0xb961b991,0xb981b98c,0xb8fcb92f,0xb96ab975,0xb892b8c8,0xb953b95e,0xb824b85c,
0x3940392f,0x383937f6,0x39613950,0x38b13876,0x39813971,0x392338eb,0x39a03991,0x398e395a,0x39bf39b0,0x39f339c1,0x39de39cf,0x3a4f3a22,0x39fb39ec,0x3aa43a7b,0x3a183a0a,0x3af03acb,
0x3a243a36,0x3ae13b07,0x39ff3a12,0x3a8b3ab7,0x39d939ec,0x3a2c3a5d,0x39b239c6,0x39c439f9,0x398a399e,0x3953398c,0x39613975,0x38d93917,0x3936394b,0x3859389a,0x390b3921,0x37a43816,
0xb901b8e6,0xb7e6b750,0xb936b91c,0xb883b83c,0xb96ab950,0xb90bb8c8,0xb99cb983,0xb98ab94b,0xb9ccb9b4,0xb9ffb9c6,0xb9fbb9e4,0xba6aba36,0xba28ba12,0xbacaba9b,0xba53ba3e,0xbb1dbaf5,
0xba57ba70,0xbb09bb33,0xba24ba3e,0xbaabbadc,0xb9efba0a,0xba40ba77,0xb9b7b9d3,0xb9c8ba05,0xb97cb99a,0xb944b988,0xb940b95e,0xb8b6b8fe,0xb901b921,0xb81eb86b,0xb8c0b8e1,0xb6fcb79e,
0x38c0389a,0x375636a7,0x390b38e6,0x38543800,0x3953392f,0x38f238a4,0x39973975,0x3985393d,0x39d939b9,0x3a0c39ca,0x3a1839f9,0x3a843a4a,0x3a533a36,0x3aed3abb,0x3a8b3a70,0x3b473b1c,
0x3b2e3b5a,0x3ba63bce,0x3aca3afe,0x3b373b74,0x3a533a91,0x3a9d3aef,0x39cc3a12,0x39de3a42,0x39363983,0x38fc3971,0x389238e6,0x37fb3880,0x37c5383c,0x35d136eb,0x3651370d,0x330934ae,
0xb6c3b5fa,0xb460b251,0xb824b788,0xb6b8b590,0xb8d9b880,0xb873b7d5,0xb981b92f,0xb96eb8f5,0xba18b9cf,0xba48b9e0,0xba9dba5d,0xbafabaa6,0xbb0fbad9,0xbb80bb43,0xbb6cbb40,0xbbd8bbb2,
0xbb51bb7d,0xbbbdbbe0,0xbae7bb1f,0xbb4ebb8c,0xba66baa9,0xbaafbb04,0xb9d1ba1e,0xb9e2ba4e,0xb928b97e,0xb8edb96c,0xb86eb8cd,0xb7afb866,0xb74bb80b,0xb54fb684,0xb5a2b679,0xb197b411,
0x362e3549,0x338330de,0x37e6370d,0x3651350e,0x38c0385c,0x38593788,0x397c3921,0x396a38e6,0x3a2439d3,0x3a5339e4,0x3ab63a70,0x3b0f3ab7,0x3b2e3af5,0x3b973b5a,0x3b8d3b61,0x3be83bc7,
0x3b703b9c,0x3bd03bef,0x3b033b3d,0x3b653ba2,0x3a793ac1,0x3ac03b19,0x39d53a2a,0x39e63a59,0x3919397a,0x38de3967,0x384938b4,0x3761384c,0x36cf37b4,0x34cc361d,0x34f035e2,0x302332e4,
0xb596b496,0xb244aecf,0xb783b690,0xb5e8b48a,0xb8a7b836,0xb83eb73a,0xb978b912,0xb965b8d7,0xba30b9d7,0xba5fb9e8,0xbacdba82,0xbb23bac8,0xbb4cbb10,0xbbacbb6f,0xbbaabb7f,0xbbf4bbd8,
0xbb8dbbb7,0xbbe0bbf9,0xbb1dbb5a,0xbb7abbb5,0xba8bbad9,0xbad0bb2d,0xb9d9ba36,0xb9eaba65,0xb90bb975,0xb8cfb963,0xb824b89a,0xb713b831,0xb651b750,0xb447b5b3,0xb43bb549,0xad58b1a4,
0x34fc33c0,0x31032bc0,0x371e3611,0x357e3405,0x388d3811,0x382436eb,0x39733903,0x396138c8,0x3a3c39db,0x3a6a39ec,0x3ae43a94,0x3b373ad9,0x3b673b2a,0x3bbe3b83,0x3bc33b9a,0x3bfc3be7,
0x3bed3bff,0x3bff3bea,0x3b8d3bc7,0x3bcc3bf5,0x3ae13b40,0x3b1d3b83,0x39ef3a70,0x39ff3a9b,0x38c0395e,0x3883394b,0x36c33816,0x357e3750,0x33833549,0x2e84332e,0x28cf3061,0xb0aca5b2,
0xaf7ea376,0x29663166,0xb514b2fd,0xb2bfad71,0xb809b69b,0xb734b555,0xb95cb8b9,0xb949b87b,0xba75b9f1,0xbaa1ba01,0xbb49bae9,0xbb8bbb25,0xbbcfbb96,0xbbf9bbd2,0xbc00bbf2,0xbbe3bbfe,
0xbbf6bc00,0xbbfcbbda,0xbb9fbbd6,0xbbd8bbfb,0xbaf0bb52,0xbb2cbb92,0xb9f3ba7b,0xba03baa6,0xb8b1b95a,0xb873b947,0xb673b7f6,0xb52cb718,0xb276b4de,0xac5eb251,0x2052ae39,0x321f2bf2,
0x2cf4a806,0xad3fb2d8,0x34a831ee,0x31e22a93,0x37db364b,0x36fc3502,0x395738a9,0x3944386b,0x3a8039f5,0x3aab3a05,0x3b5b3af8,0x3b993b33,0x3bdd3ba7,0x3bfd3bdd,0x3bff3bfa,0x3bd13bf9,
0x3bfd3bfd,0x3bf53bc6,0x3baf3be3,0x3be23bff,0x3b003b64,0x3b393ba0,0x39f73a86,0x3a083ab0,0x38a23955,0x38633942,0x362237bf,0x34d836e0,0x31663472,0x286b3172,0xaaf82b5c,0xb390ae84,
0xa8cf2cf4,0x2fc93423,0xb43bb0de,0xb103a484,0xb7a4b5fa,0xb6c3b4ae,0xb953b89a,0xb940b85c,0xba8bb9f9,0xbab6ba0a,0xbb6cbb07,0xbba6bb40,0xbbe8bbb7,0xbc00bbe7,0xbbfabbff,0xbbbabbf1,
0xbc00bbf6,0xbbebbbae,0xbbbebbed,0xbbebbc00,0xbb0fbb74,0xbb47bbad,0xb9fbba91,0xba0cbabb,0xb892b950,0xb854b93d,0xb5d1b788,0xb484b6a7,0xb055b405,0x9248b093,0x2e6ba484,0x347e3086,
0x98b6afe2,0xb128b4d8,0x339c2f97,0x3023a420,0x376c35a8,0x368a345a,0x394e388b,0x393b384c,0x3a9639fd,0x3ac03a0e,0x3b7c3b16,0x3bb33b4d,0x3bf23bc5,0x3c003bef,0x3bf03c00,0x3ba03be5,
0x3bde3b91,0x3b8a3af7,0x3bf23bff,0x3c003be3,0x3b533bb9,0x3b823bdf,0x3a103ac5,0x3a203aec,0x38443939,0x38033925,0x342f366d,0x31b03584,0xa8392f65,0xb15a1d7f,0xb531b1c9,0xb7e0b55b,
0x3269358a,0x35a83819,0xae842a61,0x205231e2,0xb651b405,0xb567b15a,0xb936b83c,0xb923b7f6,0xbacaba12,0xbaf0ba22,0xbbbebb5a,0xbbe3bb88,0xbbfdbbf5,0xbbddbc00,0xbb81bbd6,0xbadfbb7c,
0xbbcebb70,0xbb6dbac6,0xbbf8bbfb,0xbbffbbd6,0xbb60bbc4,0xbb8dbbe7,0xba14bacf,0xba24baf5,0xb834b934,0xb7e6b921,0xb3b4b634,0xb103b549,0x2c44ada3,0x326925b2,0x35e23309,0x384135f4,
0xb3a8b63a,0xb63fb869,0x2cc2ad58,0xa89db2f0,0x3617335f,0x352c30ac,0x3931382c,0x391e37d5,0x3ad43a16,0x3afa3a26,0x3bc93b66,0x3bea3b92,0x3bf93bfa,0x3bcf3bff,0x3b5f3bc5,0x3aad3b5d,
0x3bba3b4c,0x3b4d3a93,0x3bfc3bf6,0x3bfd3bc7,0x3b6c3bce,0x3b973bed,0x3a183ad9,0x3a283afe,0x3824392f,0x37c5391c,0x330935fa,0x3055350e,0xae6b2bc0,0xb377aa61,0xb690b423,0xb890b68a,
0x347236e5,0x36d438b6,0xa9fd2f7e,0x2c1233fd,0xb5dcb2b3,0xb4f0affb,0xb92db81c,0xb919b7b4,0xbaddba1a,0xbb03ba2a,0xbbd3bb72,0xbbf0bb9c,0xbbf2bbfe,0xbbbfbbfc,0xbb38bbaf,0xba77bb3c,
0xbba4bb23,0xbb2aba5b,0xbbffbbee,0xbbfabbb6,0xbb77bbd7,0xbba1bbf3,0xba1cbae2,0xba2cbb07,0xb813b92a,0xb7a4b917,0xb25db5bf,0xaf4cb4d2,0x3048a839,0x34412cf4,0x373a34c0,0x38dc371e,
0xb50eb78e,0xb767b901,0x24e9b0d1,0xadd5b484,0x35a23207,0x34b42e9d,0x3928380b,0x39143793,0x3ae73a1e,0x3b0c3a2e,0x3bdb3b7d,0x3bf53ba6,0x3be93c00,0x3bad3bf7,0x3b0d3b97,0x3a3e3b18,
0xb999b996,0xb889b85d,0xb99db99b,0xb8e0b8b5,0xb9a1b99f,0xb933b909,0xb9a6b9a4,0xb982b95b,0xb9aab9a8,0xb9cdb9a8,0xb9afb9ad,0xba15b9f2,0xb9b3b9b1,0xba58ba37,0xb9b8b9b5,0xba97ba78,
0xb9d6b9dc,0xbab0bad0,0xb9c9b9d0,0xba6bba8e,0xb9bcb9c3,0xba21ba47,0xb9afb9b5,0xb9d2b9fa,0xb9a1b9a8,0xb97db9a8,0xb994b99b,0xb924b951,0xb986b98d,0xb8c7b8f6,0xb979b980,0xb865b896,
0x3958394d,0x38403807,0x39703964,0x38ad3877,0x3986397b,0x391638e2,0x399d3992,0x39793948,0x39b339a8,0x39d639a8,0x39c939be,0x3a2d3a02,0x39df39d4,0x3a7e3a56,0x39f439e9,0x3ac73aa3,
0x3a113a1f,0x3ade3b02,0x39f43a02,0x3a903ab8,0x39d639e5,0x3a393a65,0x39b839c7,0x39da3a0b,0x399939a8,0x397439a8,0x39793989,0x3907393e,0x39583969,0x389438ce,0x39373948,0x381a3858,
0xb916b900,0xb7e8b75e,0xb941b92b,0xb87ab838,0xb96bb956,0xb8f8b8ba,0xb994b980,0xb970b935,0xb9bcb9a8,0xb9dfb9a8,0xb9e3b9d0,0xba45ba13,0xba09b9f6,0xbaa2ba74,0xba2dba1b,0xbaf4bacc,
0xba49ba5e,0xbb0abb30,0xba1dba33,0xbab3bae0,0xb9f0ba07,0xba50ba83,0xb9c0b9d8,0xb9e3ba1b,0xb990b9a8,0xb96bb9a8,0xb95db976,0xb8eab92b,0xb929b943,0xb85fb8a6,0xb8f3b90e,0xb79bb817,
0x38d138b0,0x374e36aa,0x391138f1,0x384537ee,0x394f3930,0x38db3891,0x398b396d,0x39663922,0x39c539a8,0x39e739a8,0x39fc39e1,0x3a5c3a23,0x3a313a17,0x3ac43a92,0x3a643a4b,0x3b1e3af3,
0x3a7e3a99,0x3b323b5a,0x3a453a62,0x3ad53b05,0x3a093a27,0x3a673aa0,0x39c939e9,0x39eb3a2b,0x398639a8,0x396239a8,0x39413964,0x38cc3918,0x38f8391d,0x382a387c,0x38ad38d3,0x36ff37ac,
0xb6afb5f1,0xb41ab1db,0xb80fb76a,0xb65fb540,0xb8bcb867,0xb840b775,0xb95db90e,0xb937b8bf,0xb9f0b9a8,0xba11b9a8,0xba73ba33,0xbac7ba71,0xbae5baae,0xbb57bb14,0xbb45bb17,0xbbbcbb8f,
0xbb57bb80,0xbbc6bbe6,0xbaf4bb28,0xbb63bb9b,0xba7ebabc,0xbad1bb20,0xb9f4ba3b,0xba15ba78,0xb958b9a8,0xb933b9a8,0xb8adb905,0xb830b8b5,0xb7e8b852,0xb625b748,0xb65fb726,0xb389b4f9,
0x360e3534,0x32de304e,0x37b236e3,0x35eb34b1,0x389e383d,0x3820371b,0x395438fb,0x392e38ab,0x39f839a8,0x3a1939a8,0x3a893a43,0x3adb3a7f,0x3b043ac9,0x3b6f3b2b,0x3b683b39,0x3bd03ba6,
0x3b783ba0,0x3bd93bf4,0x3b133b49,0x3b7a3bb1,0x3a933ad6,0x3ae53b36,0x39fc3a4b,0x3a1d3a87,0x394f39a8,0x392939a8,0x388e38f1,0x380f38a0,0x377a3828,0x35b136ee,0x35bc369e,0x32323469,
0xb56ab475,0xb185ad7e,0xb742b659,0xb576b420,0xb87fb812,0xb7feb6c1,0xb94ab8e7,0xb924b896,0xba00b9a8,0xba21b9a8,0xba9eba52,0xbaeeba8e,0xbb21bae3,0xbb85bb41,0xbb87bb58,0xbbe1bbbb,
0xbb96bbbc,0xbbe8bbfc,0xbb2fbb67,0xbb90bbc4,0xbaa9baf0,0xbaf7bb4b,0xba04ba5a,0xba25ba95,0xb946b9a8,0xb91fb9a8,0xb86fb8dd,0xb7ddb88c,0xb70ab7f9,0xb53ab693,0xb517b614,0xb0d7b3ae,
0x34c33365,0x302928b6,0x36d235ce,0x34ff331b,0x385f37cd,0x37bd3665,0x394138d3,0x391b3881,0x3a0939a8,0x3a2939a8,0x3ab33a62,0x3b013a9c,0x3b3d3afc,0x3b9a3b55,0x3ba33b74,0x3bef3bcd,
0x3bb03bd4,0x3bf43c00,0x3b4a3b82,0x3ba33bd5,0x3abd3b08,0x3b0a3b5f,0x3a0d3a69,0x3a2d3aa3,0x393c39a8,0x391639a8,0x385038c9,0x379b3877,0x369937a1,0x34c33637,0x346f3587,0x2ef53288,
0xad972248,0x2d6532a1,0xb487b1f4,0xb13ba91b,0xb77ab608,0xb66bb48d,0xb911b86d,0xb8eab817,0xba31b9a8,0xba50b9a8,0xbb13baaa,0xbb54bae0,0xbbacbb69,0xbbe4bbab,0xbbf8bbdc,0xbbf9bbfe,
0xbbfcbbff,0xbbf5bbc9,0xbbb5bbe3,0xbbe9bc00,0xbb1bbb72,0xbb5cbbb2,0xba35bab1,0xba54bae6,0xb90cb9a8,0xb8e5b9a8,0xb759b862,0xb648b80d,0xb44bb5da,0xb0beb45d,0xac38b160,0x2ec3a57f,
0x29b1abd9,0xb010b414,0x340e30cb,0x30421a48,0x373735ab,0x3625342c,0x39073858,0x38e03802,0x3a3939a8,0x3a5839a8,0x3b243ab8,0x3b633aed,0x3bbd3b7b,0x3bee3bb9,0x3bfe3be9,0x3bef3c00,
0x3bff3bf8,0x3be93baf,0x3bc53bee,0x3bf23c00,0x3b2c3b84,0x3b6a3bc0,0x3a3d3abf,0x3a5c3af3,0x390239a8,0x38db39a8,0x3715384d,0x360237ee,0x33a2357c,0x2f8b33f7,0x25e43036,0xb0bea3db,
0x96482f0e,0x316c34d5,0xb328af40,0xae912852,0xb6f4b54c,0xb5dfb396,0xb8fdb842,0xb8d6b7d8,0xba41b9a8,0xba60b9a8,0xbb35bac6,0xbb71baf9,0xbbccbb8c,0xbbf5bbc6,0xbc00bbf3,0xbbe2bbff,
0xbc00bbed,0xbbdabb91,0xbbd3bbf7,0xbbf8bbfd,0xbb3dbb95,0xbb78bbcb,0xba45bacc,0xba64baff,0xb8f8b9a8,0xb8d1b9a8,0xb6d2b838,0xb5bcb7c2,0xb2adb51d,0xad97b334,0x251bae14,0x32192aac,
0xa94db115,0xb2c6b593,0x32322ce7,0x2c9cac83,0x36af34ed,0x359932d2,0x38f3382d,0x38cc37ac,0x3a4939a8,0x3a6739a8,0x3b453ad3,0x3b7f3b05,0x3bd93b9d,0x3bfb3bd1,0x3bfe3bfa,0x3bd23bfb,
0x3bfc3bdd,0x3bc83b6e,0x3bdf3bfd,0x3bfd3bf8,0x3b4c3ba4,0x3b853bd6,0x3a4d3ad9,0x3a6b3b0b,0x38ee39a8,0x38c739a8,0x368d3822,0x35763796,0x31b634bd,0x2b43326f,0xac062b75,0xb371adb0,
0x340e364e,0x36a43887,0xa94d2edc,0x2d333408,0xb552b20d,0xb432ade2,0xb8c1b780,0xb899b6cc,0xba6fb9a8,0xba8cb9a8,0xbb8bbb11,0xbbb8bb3e,0xbbfebbdb,0xbbf9bbf7,0xbbbdbbf4,0xbb47bbbe,
0xbbb2bb46,0xbb35ba7c,0xbbffbbf0,0xbbf6bbb4,0xbb92bbe0,0xbbbdbbf9,0xba73bb17,0xba90bb43,0xb8bcb9a8,0xb894b9a8,0xb52fb76a,0xb40eb6b5,0xa6adb1aa,0x2e2dad1a,0x34633004,0x36f43451,
0xb4b7b705,0xb742b8d8,0x217fb099,0xaf27b499,0x350b3147,0x33d32c51,0x38b73753,0x388e369e,0x3a7639a8,0x3a9339a8,0x3b983b1d,0x3bc23b49,0x3c003be4,0x3bf33bfb,0x3ba53beb,0x3b213baa,
0x3b983b1a,0x3b0d3a3f,0x3c003be5,0x3bef3b9e,0x3b9e3be8,0x3bc63bfd,0x3a7a3b22,0x3a973b4e,0x38b239a8,0x388939a8,0x34e7373d,0x33893687,0x9cb630e4,0xb0102b11,0xb50bb12e,0xb790b4e1,
0x355e37b7,0x37dd3927,0x251b31c3,0x308d3529,0xb4c3b080,0xb340a97f,0xb8adb726,0xb884b670,0xba7eb9a8,0xba9bb9a8,0xbba3bb28,0xbbcbbb53,0xbc00bbec,0xbbebbbfe,0xbb89bbdf,0xbaf7bb93,
0xbb7abae9,0xbae1b9fe,0xbbffbbd7,0xbbe6bb86,0xbba9bbef,0xbbcfbbff,0xba81bb2e,0xba9ebb58,0xb8a8b9a8,0xb87fb9a8,0xb49fb710,0xb2f7b659,0x2884b01d,0x3109a7da,0x35b13257,0x38153570,
0xb602b832,0xb83ab972,0xaa7ab2ea,0xb185b5b6,0x347b2f72,0x32ad24b6,0x38a336f9,0x387a3642,0x3a8539a8,0x3aa239a8,0x3bae3b33,0x3bd33b5d,0x3bfd3bf2,0x3be13c00,0x3b6a3bd0,0x3acb3b79,
0x3b593ab5,0x3ab339ba,0x3bfc3bc7,0x3bdc3b6b,0x3bb33bf5,0x3bd73c00,0x3a893b39,0x3aa53b62,0x389e39a8,0x387439a8,0x345736e3,0x3263362b,0xac382eaa,0xb2011e48,0xb654b37d,0xb85fb5fd,
0xb99ab997,0xb89fb873,0xb99eb99c,0xb8f5b8ca,0xb9a3b9a0,0xb947b91e,0xb9a7b9a5,0xb995b96e,0xb9abb9a9,0xb9e0b9bb,0xb9b0b9ae,0xba26ba03,0xb9b4b9b2,0xba68ba48,0xb9b9b9b7,0xbaa6ba88,
0xb9d3b9d9,0xba9fbac0,0xb9c6b9cc,0xba59ba7d,0xb9b9b9bf,0xba0eba34,0xb9abb9b2,0xb9bdb9e6,0xb99eb9a5,0xb967b993,0xb991b997,0xb90db93b,0xb983b98a,0xb8aeb8de,0xb975b97c,0xb84cb87e,
0x395e3953,0x385c3824,0x3975396a,0x38c83892,0x398c3981,0x392f38fc,0x39a33997,0x39913961,0x39b939ae,0x39ec39bf,0x39cf39c4,0x3a423a18,0x39e439d9,0x3a913a6a,0x39f939ef,0x3ad93ab6,
0x3a0a3a18,0x3acb3af0,0x39ec39fb,0x3a7b3aa4,0x39cf39de,0x3a223a4f,0x39b039bf,0x39c139f3,0x399139a0,0x395a398e,0x39713981,0x38eb3923,0x39503961,0x387638b1,0x392f3940,0x37f63839,
0xb921b90b,0xb816b7a4,0xb94bb936,0xb89ab859,0xb975b961,0xb917b8d9,0xb99eb98a,0xb98cb953,0xb9c6b9b2,0xb9f9b9c4,0xb9ecb9d9,0xba5dba2c,0xba12b9ff,0xbab7ba8b,0xba36ba24,0xbb07bae1,
0xba3eba53,0xbaf5bb1d,0xba12ba28,0xba9bbaca,0xb9e4b9fb,0xba36ba6a,0xb9b4b9cc,0xb9c6b9ff,0xb983b99c,0xb94bb98a,0xb950b96a,0xb8c8b90b,0xb91cb936,0xb83cb883,0xb8e6b901,0xb750b7e6,
0x38e138c0,0x379e36fc,0x39213901,0x386b381e,0x395e3940,0x38fe38b6,0x399a397c,0x39883944,0x39d339b7,0x3a0539c8,0x3a0a39ef,0x3a773a40,0x3a3e3a24,0x3adc3aab,0x3a703a57,0x3b333b09,
0x3a703a8b,0x3b1c3b47,0x3a363a53,0x3abb3aed,0x39f93a18,0x3a4a3a84,0x39b939d9,0x39ca3a0c,0x39753997,0x393d3985,0x392f3953,0x38a438f2,0x38e6390b,0x38003854,0x389a38c0,0x36a73756,
0xb70db651,0xb4aeb309,0xb83cb7c5,0xb6ebb5d1,0xb8e6b892,0xb880b7fb,0xb983b936,0xb971b8fc,0xba12b9cc,0xba42b9de,0xba91ba53,0xbaefba9d,0xbafebaca,0xbb74bb37,0xbb5abb2e,0xbbcebba6,
0xbb40bb6c,0xbbb2bbd8,0xbad9bb0f,0xbb43bb80,0xba5dba9d,0xbaa6bafa,0xb9cfba18,0xb9e0ba48,0xb92fb981,0xb8f5b96e,0xb880b8d9,0xb7d5b873,0xb788b824,0xb590b6b8,0xb5fab6c3,0xb251b460,
0x367935a2,0x34113197,0x380b374b,0x3684354f,0x38cd386e,0x386637af,0x397e3928,0x396c38ed,0x3a1e39d1,0x3a4e39e2,0x3aa93a66,0x3b043aaf,0x3b1f3ae7,0x3b8c3b4e,0x3b7d3b51,0x3be03bbd,
0x3b613b8d,0x3bc73be8,0x3af53b2e,0x3b5a3b97,0x3a703ab6,0x3ab73b0f,0x39d33a24,0x39e43a53,0x3921397c,0x38e6396a,0x385c38c0,0x37883859,0x370d37e6,0x350e3651,0x3549362e,0x30de3383,
0xb5e2b4f0,0xb2e4b023,0xb7b4b6cf,0xb61db4cc,0xb8b4b849,0xb84cb761,0xb97ab919,0xb967b8de,0xba2ab9d5,0xba59b9e6,0xbac1ba79,0xbb19bac0,0xbb3dbb03,0xbba2bb65,0xbb9cbb70,0xbbefbbd0,
0xbb7fbbaa,0xbbd8bbf4,0xbb10bb4c,0xbb6fbbac,0xba82bacd,0xbac8bb23,0xb9d7ba30,0xb9e8ba5f,0xb912b978,0xb8d7b965,0xb836b8a7,0xb73ab83e,0xb690b783,0xb48ab5e8,0xb496b596,0xaecfb244,
0x3549343b,0x31a42d58,0x37503651,0x35b33447,0x389a3824,0x38313713,0x3975390b,0x396338cf,0x3a3639d9,0x3a6539ea,0x3ad93a8b,0x3b2d3ad0,0x3b5a3b1d,0x3bb53b7a,0x3bb73b8d,0x3bf93be0,
0x3b9a3bc3,0x3be73bfc,0x3b2a3b67,0x3b833bbe,0x3a943ae4,0x3ad93b37,0x39db3a3c,0x39ec3a6a,0x39033973,0x38c83961,0x3811388d,0x36eb3824,0x3611371e,0x3405357e,0x33c034fc,0x2bc03103,
0xb061a8cf,0x25b230ac,0xb549b383,0xb32eae84,0xb816b6c3,0xb750b57e,0xb95eb8c0,0xb94bb883,0xba70b9ef,0xba9bb9ff,0xbb40bae1,0xbb83bb1d,0xbbc7bb8d,0xbbf5bbcc,0xbbffbbed,0xbbeabbff,
0xbbf2bc00,0xbbfebbe3,0xbb96bbcf,0xbbd2bbf9,0xbae9bb49,0xbb25bb8b,0xb9f1ba75,0xba01baa1,0xb8b9b95c,0xb87bb949,0xb69bb809,0xb555b734,0xb2fdb514,0xad71b2bf,0xa376af7e,0x31662966,
0x2e39a052,0xabf2b21f,0x34de3276,0x32512c5e,0x37f63673,0x3718352c,0x395a38b1,0x39473873,0x3a7b39f3,0x3aa63a03,0x3b523af0,0x3b923b2c,0x3bd63b9f,0x3bfb3bd8,0x3c003bf6,0x3bda3bfc,
0x3bfa3bff,0x3bf93bd1,0x3ba73bdd,0x3bdd3bfd,0x3af83b5b,0x3b333b99,0x39f53a80,0x3a053aab,0x38a93957,0x386b3944,0x364b37db,0x350236fc,0x31ee34a8,0x2a9331e2,0xa8062cf4,0xb2d8ad3f,
0xab5c2af8,0x2e843390,0xb472b166,0xb172a86b,0xb7bfb622,0xb6e0b4d8,0xb955b8a2,0xb942b863,0xba86b9f7,0xbab0ba08,0xbb64bb00,0xbba0bb39,0xbbe3bbaf,0xbbffbbe2,0xbbfdbbfd,0xbbc6bbf5,
0xbbffbbfa,0xbbf1bbba,0xbbb7bbe8,0xbbe7bc00,0xbb07bb6c,0xbb40bba6,0xb9f9ba8b,0xba0abab6,0xb89ab953,0xb85cb940,0xb5fab7a4,0xb4aeb6c3,0xb0deb43b,0xa484b103,0x2cf4a8cf,0x34232fc9,
0x2484ae6b,0xb086b47e,0x34053055,0x30931248,0x378835d1,0x36a73484,0x39503892,0x393d3854,0x3a9139fb,0x3abb3a0c,0x3b743b0f,0x3bad3b47,0x3bed3bbe,0x3c003beb,0x3bf63c00,0x3bae3beb,
0x3c003bf0,0x3be53ba0,0x3bc53bf2,0x3bef3c00,0x3b163b7c,0x3b4d3bb3,0x39fd3a96,0x3a0e3ac0,0x388b394e,0x384c393b,0x35a8376c,0x345a368a,0x2f97339c,0xa4203023,0xafe298b6,0xb4d8b128,
0x31c93531,0x355b37e0,0xaf652839,0x9d7f315a,0xb66db42f,0xb584b1b0,0xb939b844,0xb925b803,0xbac5ba10,0xbaecba20,0xbbb9bb53,0xbbdfbb82,0xbbffbbf2,0xbbe3bc00,0xbb91bbde,0xbaf7bb8a,
0xbbd6bb81,0xbb7cbadf,0xbbf5bbfd,0xbc00bbdd,0xbb5abbbe,0xbb88bbe3,0xba12baca,0xba22baf0,0xb83cb936,0xb7f6b923,0xb405b651,0xb15ab567,0x2a61ae84,0x31e22052,0x358a3269,0x381935a8,
0xb309b5e2,0xb5f4b841,0x2da3ac44,0xa5b2b269,0x363433b4,0x35493103,0x39343834,0x392137e6,0x3acf3a14,0x3af53a24,0x3bc43b60,0x3be73b8d,0x3bfb3bf8,0x3bd63bff,0x3b703bce,0x3ac63b6d,
0x3bc53b5f,0x3b5d3aad,0x3bfa3bf9,0x3bff3bcf,0x3b663bc9,0x3b923bea,0x3a163ad4,0x3a263afa,0x382c3931,0x37d5391e,0x335f3617,0x30ac352c,0xad582cc2,0xb2f0a89d,0xb63ab3a8,0xb869b63f,
0x34233690,0x368a3890,0xabc02e6b,0x2a613377,0xb5fab309,0xb50eb055,0xb92fb824,0xb91cb7c5,0xbad9ba18,0xbafeba28,0xbbcebb6c,0xbbedbb97,0xbbf6bbfc,0xbbc7bbfd,0xbb4cbbba,0xba93bb4d,
0xbbafbb38,0xbb3cba77,0xbbfebbf2,0xbbfcbbbf,0xbb72bbd3,0xbb9cbbf0,0xba1abadd,0xba2abb03,0xb81cb92d,0xb7b4b919,0xb2b3b5dc,0xaffbb4f0,0x2f7ea9fd,0x33fd2c12,0x36e53472,0x38b636d4,
0xb4c0b73a,0xb71eb8dc,0x2839b048,0xacf4b441,0x35bf325d,0x34d22f4c,0x392a3813,0x391737a4,0x3ae23a1c,0x3b073a2c,0x3bd73b77,0x3bf33ba1,0x3bee3bff,0x3bb63bfa,0x3b233ba4,0x3a5b3b2a,
0x3b973b0d,0x3b183a3e,0x3c003be9,0x3bf73bad,0x3b7d3bdb,0x3ba63bf5,0x3a1e3ae7,0x3a2e3b0c,0x380b3928,0x37933914,0x320735a2,0x2e9d34b4,0xb0d124e9,0xb484add5,0xb78eb50e,0xb901b767,
0xb97239ba,0x39dc3996,0xb8323ab5,0x3ad0385d,0x3927b9fe,0xba1fb94d,0x37b7bae9,0xbb02b807,0xb8d83a3f,0x3a5e3900,0xb7053b1a,0x3b30375e,0x3887ba7c,0xba99b8b0,0x364ebb46,0xbb5ab6aa,
0xb90039dc,0x3a3f3972,0xad7e3be6,0x3bf83115,0x3807ba99,0xbae9b887,0xabd9bc00,0xbbfca248,0xb5f13b30,0x3b6e3705,0x32a13bed,0x3bd4b04e,0x3365bba0,0xbbc9b4d5,0xb593bbaf,0xbb803475,
0xb88739fe,0x3a99394d,0x35f13bbc,0x3b6eb414,0x3593bb1a,0xbb80b75e,0xb8b0bb02,0xba7c37b7,0xaf0e3bc9,0x3bf43365,0x3a1f39dc,0x3927b972,0xb04ebc00,0xbbed2248,0xbb30b85d,0xb7053ab5,
0xb8073a1f,0x3ae93927,0x39fe3a3f,0x394db900,0x31dbbb80,0xbbddb593,0xbb6eb832,0xb5f13ad0,0x31153c00,0x3be62248,0x3bff32a1,0x28b6bbd4,0xb7b7bb91,0xbb023534,0xbba0304e,0x34d53bed,
0xb7053a3f,0x3b303900,0x3bbc375e,0x3414bb1a,0x2248bbc9,0xbc00b365,0xbbdda8b6,0x31db3bff,0x36aa3bd4,0x3b46b2a1,0x3a7cb64e,0xb8b0bb5a,0xba1fba5e,0xb92738d8,0xb7b739fe,0x3b02394d,
0xb5f13a5e,0x3b6e38d8,0x3bd42bd9,0xb2a1bbfc,0xb115bbf4,0xbbe6af0e,0xb9dc375e,0x39723b1a,0x39273b46,0x3a1fb6aa,0x3475bad0,0xbbafb832,0xbb91b887,0xb5343a99,0x34143c00,0x3bbc2248,
0xb4d53a7c,0x3ba038b0,0x3a3fb593,0xb900bb80,0xb534bc00,0xbb912248,0xb4143ab5,0x3bbc385d,0x3a993a5e,0x3887b8d8,0xb5f1bbfc,0xbb6e2bd9,0xbbffb475,0x28b63baf,0x3ad03a1f,0x3832b927,
0xb3653a99,0x3bc93887,0x36aab996,0xbb46b9ba,0xb7b7bbed,0xbb02304e,0x34d53bfc,0x3ba02bd9,0x3b913927,0x3534ba1f,0xbae9ba3f,0xb8073900,0xbb5a28b6,0x364e3bff,0x3bd43115,0xb2a1bbe6,
0xb1153ab5,0x3be6385d,0xa8b6bb6e,0xbbffb5f1,0xb900bbbc,0xba3f3414,0x3a1f3b30,0x3927b705,0x3bfc375e,0x2bd9bb1a,0xbbedb475,0x304e3baf,0xb9ba3593,0x39963b80,0x3887b832,0xba99bad0,
0xad7e3ad0,0x3bf83832,0xb7b7bbff,0xbb0228b6,0xb9febb6e,0xb94d35f1,0x3bed3887,0x304eba99,0x3bd43414,0xb2a1bbbc,0xb9963534,0x39ba3b91,0xb6aa3900,0x3b463a3f,0xb115bba0,0xbbe6b4d5,
0xa2483ae9,0x3c003807,0xba99bb30,0xb8873705,0xbad0bb02,0xb83237b7,0x3b462d7e,0xb6aabbf8,0x3b1a28b6,0xb75ebbff,0xaf0e3a7c,0x3bf438b0,0xabd93ab5,0x3bfc385d,0xba5ebb5a,0xb8d8364e,
0x2bd93b02,0x3bfc37b7,0xbbedb927,0xb04e3a1f,0xbb6eba7c,0xb5f138b0,0x385db6aa,0xbab5bb46,0x39dcb1db,0xb972bbdd,0x38323c00,0x3ad02248,0x34d53bbc,0x3ba03414,0xbbf4b705,0x2f0e3b30,
0x304e3b1a,0x3bed375e,0xbb91b475,0x35343baf,0xbbd4b9dc,0xb2a13972,0x2248ba7c,0xbc00b8b0,0x3832b64e,0xbad0bb5a,0x3b803a99,0x3593b887,0x39003bfc,0x3a3fabd9,0xb9273414,0x3a1f3bbc,
0x32a13b30,0x3bd43705,0xb996304e,0x39ba3bed,0xbbffb927,0xa8b63a1f,0xb832bbf4,0xbad0af0e,0x3475b8b0,0xbbafba7c,0x3ba03593,0xb4d5bb80,0x3ae93b6e,0x3807b5f1,0x2bd93a99,0x3bfc3887,
0x34753b46,0x3baf36aa,0xb4d53832,0x3ba03ad0,0xbbedb85d,0x304e3ab5,0xbb30bb5a,0xb705364e,0x2248b9fe,0xbc00b94d,0x3887b414,0xba99bbbc,0x3be63a1f,0x3115b927,0x39dc3bf4,0x3972af0e,
0x35933b5a,0x3b80364e,0x31153a99,0x3be63887,0xbba0b705,0x34d53b30,0xbbf4b8d8,0x2f0e3a5e,0xb414bb02,0xbbbcb7b7,0xabd9ba1f,0xbbfcb927,0x3bd43832,0xb2a1bad0,0x3c003972,0xa248b9dc,
0x36aa3b6e,0x3b4635f1,0x38b03bdd,0x3a7c31db,0xbb1ab534,0x375e3b91,0xba3fb04e,0x39003bed,0xb807bbaf,0xbae9b475,0xb94dbbf8,0xb9fead7e,0x3ab53365,0xb85dbbc9,0x39ba28b6,0xb996bbff,
0x37b73b80,0x3b023593,0x3b1a3bc9,0x375eb365,0xba5eb2a1,0x38d83bd4,0xb53435f1,0x3b913b6e,0xb9babbfc,0xb996abd9,0xbbddbae9,0xb1db3807,0x38b0ad7e,0xba7cbbf8,0x28b6b900,0xbbffba3f,
0x385d3b91,0x3ab53534,0x3c003a5e,0x2248b8d8,0xb972ad7e,0x39dc3bf8,0x33653a3f,0x3bc93900,0xbb02bbe6,0xb7b73115,0xbb1ab6aa,0x375e3b46,0x3414b64e,0xbbbcbb5a,0xb94dbbdd,0xb9feb1db,
0x38d83ba0,0x3a5e34d5,0x3b3037b7,0xb705bb02,0xb85d28b6,0x3ab53bff,0x39ba3be6,0x39963115,0xbbc9bb6e,0xb36535f1,0xb6aa31db,0x3b463bdd,0xaf0eb94d,0xbbf4b9fe,0xbbf8bae9,0xad7e3807,
0x394d3baf,0x39fe3475,0x38d82d7e,0xba5ebbf8,0xb64e3115,0x3b5a3be6,0x3bd43b80,0x32a1b593,0xbbffba99,0x28b63887,0x336539ba,0x3bc93996,0xb75ebae9,0xbb1ab807,0xba3fb534,0x39003b91,
0x39ba3bbc,0x39963414,0x31dbb534,0xbbddbb91,0xb3653475,0x3bc93baf,0x3b803927,0xb593ba1f,0xbba0b972,0x34d539dc,0x3a3f3be6,0x39003115,0xb9febbd4,0xb94db2a1,0xb04e35f1,0x3bed3b6e,
0x3a1f3bc9,0x39273365,0xb475b972,0xbbafb9dc,0xabd9364e,0x3bfc3b5a,0x38d831db,0xba5ebbdd,0xbab5b807,0x385d3ae9,0x3c003b30,0x2248b705,0xbb80bbf4,0xb5932f0e,0x38b03b1a,0x3a7c375e,
0x3a7c3bd4,0x38b032a1,0xb972bb5a,0xb9dcb64e,0x2f0e3807,0x3bf43ae9,0x2d7eb534,0xbbf8bb91,0xb94db4d5,0x39fe3ba0,0x3a5e37b7,0xb8d8bb02,0xbc00bb46,0x224836aa,0x3bdd3bc9,0x31dbb365,
0x3ad03bdd,0x383231db,0xbb80bc00,0xb5932248,0x347538d8,0x3baf3a5e,0xb75eb9fe,0xbb1ab94d,0xb705ad7e,0x3b303bf8,0x3414af0e,0xbbbcbbf4,0xbb6eb9dc,0x35f13972,0x3ab538b0,0xb85dba7c,
0x3b1a3be6,0x375e3115,0xbbf4bb46,0x2f0e36aa,0x37053996,0x3b3039ba,0xbae9bbd4,0xb807b2a1,0xb1db304e,0x3bdd3bed,0xb64eb94d,0xbb5ab9fe,0xb9dcb7b7,0x39723b02,0x3365ad7e,0xbbc9bbf8,
0x3b5a3bed,0x364e304e,0xbab5b94d,0x385d39fe,0x38b03a3f,0x3a7c3900,0xbbffbba0,0x28b634d5,0x2d7e3593,0x3bf83b80,0xbb02bbc9,0xb7b7b365,0xb705b1db,0x3b303bdd,0xb807b9ba,0xbae9b996,
0x3b913bf4,0x35342f0e,0xb807b4d5,0x3ae93ba0,0x39ba3ad0,0x39963832,0xba99b972,0x388739dc,0x3593385d,0x3b803ab5,0xbbe6bb6e,0x311535f1,0xad7e304e,0x3bf83bed,0xbbafbbfc,0xb475abd9,
0x3bbc3bf8,0x34142d7e,0xabd92f0e,0x3bfc3bf4,0x3a993b46,0x388736aa,0xb64eb365,0x3b5a3bc9,0x38b039ba,0x3a7c3996,0xb972b85d,0x39dc3ab5,0x34753705,0x3baf3b30,0xbb1aba5e,0x375e38d8,
0x3bdd3bfc,0x31db2bd9,0x364e3807,0x3b5a3ae9,0x3b463ba0,0x36aa34d5,0x31153475,0x3be63baf,0x3a3f3ad0,0x39003832,0xad7e28b6,0x3bf83bff,0x38d83996,0x3a5e39ba,0xb534b2a1,0x3b913bd4,
0x3bf43bff,0x2f0e28b6,0x3a1f3a7c,0x392738b0,0x3bbc3bdd,0x341431db,0x394d39ba,0x39fe3996,0x3b5a3b91,0x364e3534,0x385d38d8,0x3ab53a5e,0x3ad03b1a,0x3832375e,0x36aa37b7,0x3b463b02,
0x3bff3c00,0x28b62248,0x3bc93bd4,0x336532a1,0x3bf83bfc,0x2d7e2bd9,0x3baf3bbc,0x34753414,0x3bed3bf4,0x304e2f0e,0x3b913ba0,0x353434d5,0x3bdd3be6,0x31db3115,0x3b6e3b80,0x35f13593,
0xb5933b6e,0x3b8035f1,0xb1153bdd,0x3be631db,0x34d5bb91,0xbba0b534,0x2f0ebbed,0xbbf4b04e,0xb4143baf,0x3bbc3475,0xabd93bf8,0x3bfc2d7e,0x32a1bbc9,0xbbd4b365,0x2248bbff,0xbc00a8b6,
0x37b73b46,0x3b02b6aa,0x3b1a3832,0x375ebad0,0xb8d8bab5,0xba5e385d,0xbb91b64e,0xb5343b5a,0x39ba39fe,0x3996b94d,0x3bdd3414,0x31dbbbbc,0xba7cb927,0xb8b03a1f,0xbbffaf0e,0xa8b63bf4,
0x3bd43534,0x32a1bb91,0x39bab8d8,0xb996ba5e,0xbbffad7e,0x28b63bf8,0xb8323a3f,0x3ad03900,0x3bafb115,0xb475bbe6,0x34d5bb46,0xbba0b6aa,0xbae9364e,0x38073b5a,0xabd93bdd,0x3bfc31db,
0x3a5eb75e,0xb8d8bb1a,0xb705bbaf,0xbb303475,0xb85d39dc,0x3ab53972,0x39ba3a7c,0x3996b8b0,0x3365bb5a,0xbbc9b64e,0xbb46b887,0xb6aa3a99,0x2f0e3bfc,0x3bf42bd9,0x3bf83414,0x2d7ebbbc,
0x2bd9bbaf,0xbbfcb475,0xbbedad7e,0x304e3bf8,0x35f13be6,0x3b6eb115,0x3ab5b593,0xb85dbb80,0xb9dcba99,0xb9723887,0xb83239ba,0x3ad03996,0x3ba03807,0x34d5bae9,0x2f0ebb91,0xbbf4b534,
0xb9babae9,0xb9963807,0xb1db3b30,0x3bdd3705,0x3bc937b7,0x3365bb02,0xb593bbf8,0xbb802d7e,0xbba028b6,0x34d53bff,0x3a3f3a7c,0x3900b8b0,0x394db85d,0xb9febab5,0xbbedb64e,0xb04e3b5a,
0xbbf8b365,0x2d7e3bc9,0x3b0239dc,0x37b7b972,0x39feb64e,0xb94dbb5a,0xbbedb1db,0x304e3bdd,0xb2a13ae9,0x3bd43807,0x39bab705,0xb996bb30,0xb6aabbf4,0xbb462f0e,0xb1153b1a,0x3be6375e,
0xb8b0385d,0x3a7c3ab5,0x39dcb5f1,0xb972bb6e,0xaf0ebbbc,0xbbf4b414,0xad7e3b30,0x3bf83705,0x39fe3b1a,0x394db75e,0xb8d8bbaf,0xba5e3475,0xbc00b593,0x22483b80,0x3bdd3832,0x31dbbad0,
0x33653bdd,0x3bc931db,0xb6aabc00,0xbb462248,0xbb02ba5e,0xb7b738d8,0x3ba0394d,0x34d5b9fe,0x3b912d7e,0xb534bbf8,0xbae92f0e,0x38073bf4,0xb64e3972,0x3b5a39dc,0x32a1ba7c,0xbbd4b8b0,
0x3b1a3a7c,0x375eb8b0,0xbbf4b593,0x2f0e3b80,0xbb30a248,0x37053c00,0x3807b85d,0xbae9bab5,0x31dbba5e,0xbbddb8d8,0x364e3bfc,0x3b5a2bd9,0x39723baf,0x39dcb475,0xbbc9b927,0xb3653a1f,
0x3b6e304e,0xb5f1bbed,0xb2a139fe,0x3bd4394d,0xb1153a3f,0x3be63900,0xb9dcbba0,0xb97234d5,0xba1fbb80,0xb9273593,0x3baf3365,0xb475bbc9,0x3b9131db,0xb534bbdd,0xb41439ba,0x3bbc3996,
0x3534b900,0xbb91ba3f,0x3ae93b1a,0x3807b75e,0x39ba3bc9,0x3996b365,0xba9928b6,0x38873bff,0xbb80b2a1,0x35933bd4,0xb115bb5a,0xbbe6b64e,0x2d7eba5e,0xbbf8b8d8,0x3baf39fe,0x3475b94d,
0xb807bbf8,0xbae9ad7e,0x39feaf0e,0xb94dbbf4,0x3bdd36aa,0xb1dbbb46,0x35f13bc9,0x3b6e3365,0xb11539ba,0x3be63996,0xbbffb85d,0x28b63ab5,0xbb02bb30,0xb7b73705,0x34d5b8d8,0xbba0ba5e,
0xbbddb9fe,0xb1db394d,0xb64ebbbc,0xbb5ab414,0x36aab75e,0xbb46bb1a,0x3be637b7,0xb115bb02,0x3a3f3bc9,0x3900b365,0xad7e39dc,0x3bf83972,0xba5ea248,0x38d83c00,0xbb91bab5,0xb534385d,
0xba3fa8b6,0x39003bff,0xbbf8b8b0,0x2d7e3a7c,0xb807bbdd,0xbae9b1db,0x2bd9b9ba,0xbbfcb996,0x3b6e3534,0xb5f1bb91,0x3bd43a5e,0x32a1b8d8,0x33653b1a,0x3bc9375e,0xb59337b7,0x3b803b02,
0xa8b63996,0x3bff39ba,0xb365385d,0x3bc93ab5,0xbbf8b9fe,0xad7e394d,0xbbafbae9,0xb4753807,0x304eb900,0xbbedba3f,0x3534b75e,0xbb91bb1a,0x3bdd3a7c,0x31dbb8b0,0x3b6e3b46,0x35f1b6aa,
0x39dc3c00,0x3972a248,0x3ad03bd4,0x3832b2a1,0xb9272bd9,0x3a1f3bfc,0xb7b73414,0x3b023bbc,0xba5ebbf4,0xb8d82f0e,0xbb30bba0,0xb70534d5,0x3887b115,0xba99bbe6,0x364eb593,0xbb5abb80,
0x3bf43972,0xaf0eb9dc,0x3a1f3115,0xb927bbe6,0x34143a99,0x3bbc3887,0x39fe3c00,0x394d2248,0xbb5ab705,0x364e3b30,0xb85d304e,0x3ab53bed,0xb832bba0,0xbad0b4d5,0xbb46bbaf,0xb6aa3475,
0x3887abd9,0xba99bbfc,0xb5f1bae9,0xbb6eb807,0x3b803ba0,0x3593b4d5,0x3a7c3475,0xb8b0bbaf,0xaf0e3832,0x3bf43ad0,0x3a1f3bff,0x392728b6,0xbbedb996,0x304e39ba,0xb70532a1,0x3b303bd4,
0xb414ba1f,0xbbbcb927,0xbbfcba3f,0x2bd93900,0x3a993593,0xb887bb80,0xb64ebad0,0xbb5ab832,0x3a7c3c00,0x38b02248,0x39dc32a1,0xb972bbd4,0xb4753534,0x3baf3b91,0x3b1a3bed,0x375eb04e,
0xbb30bbf4,0xb7052f0e,0xb41434d5,0x3bbc3ba0,0x2248b832,0xbc00bad0,0xbbddb9dc,0x31db3972,0x3b46385d,0xb6aabab5,0xb8b0bb6e,0xba7cb5f1,0x3a1f3bed,0x3927304e,0x37b7abd9,0xbb02bbfc,
0xbb5ab8d8,0x364e3a5e,0x3ab53bfc,0x385d2bd9,0xba7cbbf4,0xb8b0af0e,0xa8b6375e,0x3bff3b1a,0x2d7eb6aa,0xbbf8bb46,0xbb02b832,0x37b73ad0,0x3b303887,0xb705ba99,0xbae9bc00,0xb807a248,
0xb4d53115,0x3ba03be6,0x3a3f36aa,0xb900bb46,0xbb91b996,0x353439ba,0x3bbc3bd4,0x3414b2a1,0xba99bbed,0xb887b04e,0x35f139fe,0x3b6e394d,0xa8b6b7b7,0xbbffbb02,0xb832ad7e,0x3ad03bf8,
0x38323a99,0x3ad03887,0xb593b996,0xbb80b9ba,0xb475304e,0x3baf3bed,0x375e2bd9,0xbb1abbfc,0xbb30b927,0x37053a1f,0x3bbc3a3f,0xb414b900,0xbb6ebbff,0xb5f128b6,0x3ab53be6,0x385d3115,
0x3be63bd4,0x3115b2a1,0xbbffbb5a,0x28b6364e,0x39003ae9,0x3a3f3807,0xba1fbb91,0xb927b534,0xabd934d5,0x3bfc3ba0,0xb04eb7b7,0xbbedbb02,0xb9bab6aa,0x39963b46,0x38873365,0xba99bbc9,
0x3a1f3832,0xb927bad0,0xb47528b6,0x3baf3bff,0x3bfc3b6e,0xabd9b5f1,0xba5eb887,0x38d83a99,0x3ab53bbc,0x385d3414,0xbc00bb91,0x22483534,0x35933900,0x3b803a3f,0xba7cbba0,0xb8b0b4d5,
0x2248b414,0xbc00bbbc,0x3a993b91,0x38873534,0x38323475,0xbad0bbaf,0x36aa3927,0x3b463a1f,0x3b1a39dc,0xb75eb972,0xaf0e3115,0x3bf43be6,0x3bfc3bd4,0x2bd9b2a1,0xb8d8b5f1,0x3a5e3b6e,
0xb9febb02,0xb94db7b7,0x3a5e3927,0xb8d8ba1f,0xb64eb8b0,0xbb5aba7c,0x3bd43b46,0xb2a1b6aa,0x28b6b1db,0xbbffbbdd,0x3bc93c00,0x33652248,0x375e3414,0xbb1abbbc,0x3a3f3b30,0x39003705,
0xbbedbba0,0x304e34d5,0xb534b7b7,0xbb91bb02,0xbbd4bbff,0xb2a1a8b6,0x2248b115,0xbc00bbe6,0xbad0bb6e,0xb832b5f1,0x359331db,0xbb80bbdd,0xb900b9fe,0xba3fb94d,0x39273807,0xba1fbae9,
0xb85db705,0x3ab53b30,0xbc00bbed,0x2248304e,0xb9dcb927,0x39723a1f,0xbbc9bbf4,0xb365af0e,0xbb02ba7c,0x37b738b0,0xbb1abb80,0xb75eb593,0xbbbcbb6e,0x341435f1,0xb9feba99,0xb94db887,
0x34753593,0x3baf3b80,0xb4d5b365,0x3ba03bc9,0x304e32a1,0x3bed3bd4,0xb705b5f1,0x3b303b6e,0xa2482bd9,0x3c003bfc,0xb887b807,0x3a993ae9,0xb115ad7e,0x3be63bf8,0xb972b900,0x39dc3a3f,
0x3b463b5a,0x36aa364e,0x3a7c3a99,0x38b03887,0x3b1a3b30,0x375e3705,0x3a3f3a5e,0x390038d8,0x3ae93b02,0x380737b7,0x39fe3a1f,0x394d3927,0x3ab53ad0,0x385d3832,0x39ba39dc,0x39963972,
0x28b63c00,0x3bffa248,0x33653bd4,0x3bc9b2a1,0xad7ebbfc,0xbbf82bd9,0xb475bbbc,0xbbaf3414,0x304e3bf4,0x3bedaf0e,0x35343ba0,0x3b91b4d5,0xb1dbbbe6,0xbbdd3115,0xb5f1bb80,0xbb6e3593,
0x3bf4a8b6,0xaf0ebbff,0x3a1fb8b0,0xb927ba7c,0xbbbc31db,0x34143bdd,0xb94d3996,0x39fe39ba,0x3b5ab534,0xb64ebb91,0x385dba5e,0xbab5b8d8,0xbad0375e,0x38323b1a,0xb6aa3b02,0x3b4637b7,
0xb1dbbbfc,0xbbdd2bd9,0xbb5ab807,0xb64e3ae9,0x36aa3ba0,0x3b46b4d5,0x3be63475,0x3115bbaf,0xb900bad0,0xba3f3832,0xbbf8a8b6,0x2d7e3bff,0x3a5e3996,0x38d8b9ba,0x3b91b2a1,0xb534bbd4,
0xbbbc2d7e,0x34143bf8,0x2bd93bf4,0x3bfc2f0e,0x3a99b6aa,0xb887bb46,0xb64ebbc9,0xbb5a3365,0xb8b03996,0x3a7c39ba,0x39723ab5,0x39dcb85d,0x3475bb30,0xbbafb705,0xbb1ab8d8,0xb75e3a5e,
0x35343bf4,0x3b91af0e,0x3ae9b4d5,0xb807bba0,0xb996bad0,0xb9ba3832,0xb8873972,0x3a9939dc,0x3b80385d,0x3593bab5,0x3115bb6e,0xbbe6b5f1,0xbbf8b04e,0x2d7e3bed,0x34753bfc,0x3bafabd9,
0x3b5ab04e,0xb64ebbed,0xbab5b9fe,0xb85d394d,0xb8b03900,0x3a7c3a3f,0x3bff34d5,0x28b6bba0,0x2d7ebb80,0xbbf8b593,0xbb023365,0x37b73bc9,0x37053bdd,0x3b30b1db,0x3807b996,0xbae9b9ba,
0xb75ebbe6,0xbb1a3115,0xaf0e3b46,0x3bf436aa,0x3b303996,0x3705b9ba,0xb807bbd4,0xbae932a1,0xbbddb04e,0x31db3bed,0x3b5a394d,0x364eb9fe,0x3972b7b7,0xb9dcbb02,0xbbc9ad7e,0x33653bf8,
0xbad031db,0x38323bdd,0x3b802248,0xb593bc00,0x3475ba5e,0xbbafb8d8,0xb75e394d,0x3b1a39fe,0x37053bf8,0x3b30ad7e,0xb414bbf4,0xbbbcaf0e,0xbb6eb972,0xb5f139dc,0x3ab53a7c,0x385db8b0,
0x38b03bd4,0x3a7cb2a1,0xb9dcbb5a,0xb972364e,0xbbf4b807,0xaf0e3ae9,0x3bf83534,0xad7ebb91,0x39feb4d5,0xb94dbba0,0xb8d837b7,0x3a5e3b02,0xa2483b46,0x3c0036aa,0xb1dbbbc9,0xbbddb365,
0x3a1fb365,0xb927bbc9,0xb47539dc,0x3baf3972,0x2bd93b5a,0x3bfc364e,0xb8d8bbdd,0xba5e31db,0xbab5bae9,0xb85d3807,0x3c003705,0xa248bb30,0x3b802f0e,0xb593bbf4,0xb8b0375e,0x3a7c3b1a,
0xb996bbbc,0xb9ba3414,0x3bdd3534,0xb1dbbb91,0x3bc93475,0xb365bbaf,0xb5933927,0x3b803a1f,0xb4d53972,0x3ba039dc,0xb900bbe6,0xba3f3115,0xb94dbbd4,0xb9fe32a1,0x3bed35f1,0xb04ebb6e,
0xb94d3475,0x39fe3baf,0xb8d8bbf8,0xba5e2d7e,0xb64ebbe6,0xbb5ab115,0x3bd43593,0xb2a1bb80,0x3bff3887,0x28b6ba99,0xb3653996,0x3bc939ba,0xb75e3807,0x3b1a3ae9,0xba3fbb91,0xb9003534,
0x3a5e3ba0,0x38d8b4d5,0xb70537b7,0x3b303b02,0xbab5a8b6,0x385d3bff,0xb996bbe6,0xb9ba3115,0xb365bb6e,0xbbc9b5f1,0x3b4631db,0xb6aabbdd,0x3bf4394d,0x2f0eb9fe,0x2d7e3ae9,0x3bf83807,
0x385db534,0xbab5bb91,0x3c0038d8,0xa248ba5e,0x39723bf8,0x39dcad7e,0xb3653900,0x3bc93a3f,0xbb02b115,0x37b73be6,0xbb1abb46,0xb75e36aa,0xb414bb5a,0xbbbcb64e,0x394db1db,0xb9febbdd,
0xbb02bb80,0xb7b73593,0xb75ebbc9,0xbb1ab365,0x38d8b2a1,0xba5ebbd4,0x3b9135f1,0xb534bb6e,0x39963bfc,0x39baabd9,0x31db3ae9,0x3bdd3807,0xba7cad7e,0x38b03bf8,0xbbffb900,0x28b63a3f,
0xb6aa35f1,0x3b463b6e,0xb8b031db,0x3a7c3bdd,0xbb1abb91,0xb75e3534,0xba3fbbed,0xb900304e,0x3807b475,0xbae9bbaf,0x394dad7e,0xb9febbf8,0x3ab53bc9,0x385db365,0x39ba3bff,0x3996a8b6,
0x3b803b5a,0x3593b64e,0x3be63a99,0x3115b887,0xb4d53705,0x3ba03b30,0xaf0e38d8,0x3bf43a5e,0xbbbcbb02,0xb41437b7,0xbbfcba1f,0xabd93927,0x32a1b832,0xbbd4bad0,0x2248b972,0xbc00b9dc,
0x3475b6aa,0xbbafbb46,0xb4d5bad0,0xbba0b832,0x3bed3ab5,0x304eb85d,0x3b30364e,0xb705bb5a,0x2248394d,0x3c0039fe,0x38873bbc,0x3a993414,0xbbe6b927,0x31153a1f,0xb9dcaf0e,0x39723bf4,
0xbbd4bb30,0xb2a13705,0xb9bab04e,0x39963bed,0xa8b6b927,0xbbffba1f,0xbad0bbf4,0xb8322f0e,0x3baf38b0,0xb475ba7c,0x34d5b593,0xbba0bb80,0x38073b6e,0x3ae935f1,0x3bfc3a99,0x2bd9b887,
0xb04e375e,0x3bed3b1a,0x3b913baf,0x3534b475,0xbbd4b972,0x32a139dc,0x224838b0,0x3c003a7c,0xb832bb5a,0xbad0b64e,0xbb80b887,0x35933a99,0x39002bd9,0xba3fbbfc,0xb927bbbc,0xba1fb414,
0x3bfc3b02,0x2bd9b7b7,0xb04eb927,0xbbedba1f,0x35f13a7c,0x3b6e38b0,0x3ab536aa,0xb85dbb46,0xb972b1db,0x39dc3bdd,0x3ad03c00,0x3832a248,0xbba0bbbc,0xb4d53414,0xaf0e3705,0x3bf43b30,
0xa248b807,0xbc00bae9,0xba99b705,0x38873b30,0x3ad037b7,0xb832bb02,0xbb46bbf8,0xb6aa2d7e,0x3b1a3bff,0x375ea8b6,0xaf0eb8b0,0xbbf4ba7c,0x2bd9385d,0x3bfc3ab5,0x3a5e364e,0xb8d8bb5a,
0xbbf8bad0,0x2d7e3832,0x3b023bff,0x37b728b6,0xb94dbb6e,0xb9feb5f1,0x304e3887,0x3bed3a99,0x32a1b414,0xbbd4bbbc,0xb9bab534,0x39963b91,0x3b463900,0xb6aaba3f,0xbbe6bba0,0xb11534d5,
0x3115385d,0x3be63ab5,0x28b6b5f1,0xbbffbb6e,0xb900b414,0x3a3f3bbc,0x3a1f3705,0xb927bb30,0xbbfcbb1a,0x2bd9375e,0x3bed3baf,0x304eb475,0xb9babb80,0xb996b593,0x38873ad0,0x3a993832,
0x3bc93a99,0xb365b887,0xbb46b996,0x36aa39ba,0x3b023bed,0x37b7304e,0xbba0bbfc,0xb4d52bd9,0x35343927,0x3b913a1f,0xb807ba3f,0xbae9b900,0xb64ea8b6,0x3b5a3bff,0x32a1b115,0xbbd4bbe6,
0xb4d5b8b0,0xbba0ba7c,0x3a3f3b80,0x39003593,0x35342248,0xbb91bc00,0x3414385d,0x3bbc3ab5,0x3a9938d8,0xb887ba5e,0xb5f1abd9,0x3b6e3bfc,0x3bff3baf,0x28b6b475,0xbad0b927,0x38323a1f,
0xbb6eba5e,0x35f138d8,0x32a1abd9,0xbbd4bbfc,0xbbe6bbf4,0xb1152f0e,0x3972375e,0xb9dcbb1a,0xba1fbb46,0xb927b6aa,0x3baf3ad0,0xb475b832,0xb534b887,0xbb91ba99,0x3bbc3c00,0x3414a248,
0x37053900,0x3b303a3f,0xbbbcbb1a,0x3414375e,0x22483365,0x3c003bc9,0xbbddbbff,0xb1db28b6,0xb6aab2a1,0x3b463bd4,0xba7cbb5a,0xb8b0b64e,0xba1fb8d8,0x39273a5e,0xb7b7b94d,0xbb02b9fe,
0x3ae93a1f,0xb807b927,0x394d3a3f,0x39fe3900,0x3bdd3b80,0xb1dbb593,0x35f13832,0x3b6e3ad0,0x3be63c00,0x3115a248,0x28b632a1,0x3bff3bd4,0x3b023b91,0x37b73534,0xb4d5b04e,0x3ba03bed,
0xb887b94d,0xba99b9fe,0x35f13414,0xbb6ebbbc,0xb593b75e,0xbb80bb1a,0x38b037b7,0xba7cbb02,0xaf0eb365,0xbbf4bbc9,0x3a1f3972,0xb927b9dc,0x304e2248,0xbbedbc00,0x3b303ab5,0xb705b85d,
0xba3fb9dc,0x39003972,0xbbf8bbe6,0x2d7e3115,0xbae9ba99,0x38073887,0xbbfcbc00,0xabd92248,0xbb6ebb30,0x35f13705,0xbbd4bbed,0xb2a1b04e,0xbbc9bba0,0x336534d5,0xbb80bbaf,0xb593b475,
0x39723996,0x39dc39ba,0x3832385d,0x3ad03ab5,0x3927394d,0x3a1f39fe,0x37b73807,0x3b023ae9,0x38d83900,0x3a5e3a3f,0x3705375e,0x3b303b1a,0x388738b0,0x3a993a7c,0x364e36aa,0x3b5a3b46,
0x36aa3b5a,0x3b46b64e,0x38b03a99,0x3a7cb887,0xb75ebb30,0xbb1a3705,0xb900ba5e,0xba3f38d8,0x38073b02,0x3ae9b7b7,0x394d3a1f,0x39feb927,0xb85dbad0,0xbab53832,0xb996b9dc,0xb9ba3972,
0x3475bb80,0xbbafb593,0xb4d5bbc9,0xbba03365,0xb04e3bd4,0x3bed32a1,0x37053b6e,0x3b30b5f1,0xa248bbfc,0xbc00abd9,0xb887bae9,0xba993807,0x31153bf8,0x3be6ad7e,0x39723a3f,0x39dcb900,
0xbab53705,0x385d3b30,0xa2483bed,0x3c00304e,0x3972b927,0xb9dcba1f,0xb365bbf4,0xbbc92f0e,0xb7b73a7c,0x3b0238b0,0x375e3b80,0x3b1ab593,0x3414bb6e,0xbbbcb5f1,0xb94dba99,0xb9fe3887,
0x3bed34d5,0x304ebba0,0x3534bb02,0xbb91b7b7,0xbbd428b6,0x32a13bff,0x22483be6,0x3c003115,0x3ad0b5f1,0xb832bb6e,0xb593bbdd,0xbb8031db,0xb900394d,0x3a3f39fe,0x39273ae9,0x3a1fb807,
0xb94dbb02,0xb9fe37b7,0xb8d83927,0x3a5e3a1f,0x3b5a38b0,0x364eba7c,0x32a1bb46,0xbbd4b6aa,0xbbffb1db,0x28b63bdd,0x33653c00,0x3bc9a248,0x3b1ab414,0xb75ebbbc,0xb900bb30,0xba3f3705,
0x22483bbc,0x3c003414,0x3a99b534,0xb887bb91,0xb832bbaf,0xbad03475,0xb6aa3a1f,0x3b463927,0x3b1a3972,0x375eb9dc,0xaf0ebbe6,0xbbf4b115,0xbbfcb2a1,0x2bd93bd4,0x38d83b6e,0x3a5eb5f1,
0x3927b832,0xba1fbad0,0xbbafa8b6,0x34753bff,0xabd93b6e,0x3bfc35f1,0x38d8b887,0xba5eba99,0xb85dbbbc,0xbab53414,0xa2483b91,0x3c003534,0x3b803900,0x3593ba3f,0xb8b0bba0,0xba7c34d5,
0xbbe6b2a1,0x31153bd4,0x3bff364e,0x28b6bb5a,0x3900b807,0xba3fbae9,0xba1f3534,0x39273b91,0x2bd93ba0,0x3bfc34d5,0x304ebb02,0xbbedb7b7,0xb9babb46,0xb99636aa,0x38873bc9,0x3a99b365,
0x3ad03a99,0x3832b887,0xbb80b996,0xb59339ba,0xbbafb04e,0x34753bed,0x3b1aabd9,0xb75ebbfc,0x3705b927,0xbb30ba1f,0xb4143a3f,0x3bbc3900,0x35f13bff,0x3b6e28b6,0xb85dbbe6,0xbab53115,
0xb4d5bbe6,0xbba0b115,0x3a3f3b46,0x3900b6aa,0x3b9139ba,0x3534b996,0xbbbcb2a1,0x34143bd4,0xba99304e,0x38873bed,0x35f1b94d,0xbb6eb9fe,0x28b6bb02,0xbbffb7b7,0x38323bf8,0x3ad0ad7e,
0xb64e38d8,0x3b5a3a5e,0xb85dbbfc,0xbab52bd9,0xb8b0bbf4,0xba7c2f0e,0x3bff375e,0xa8b6bb1a,0x3bf836aa,0xad7ebb46,0xb7b73832,0x3b023ad0,0xb7053887,0x3b303a99,0xb807bc00,0xbae92248,
0x3b302f0e,0xb705bbf4,0x34143ba0,0x3bbc34d5,0x22483ad0,0x3c003832,0xbbddb972,0xb1db39dc,0xbb46bab5,0xb6aa385d,0x38b0b5f1,0xba7cbb6e,0x3a1fb04e,0xb927bbed,0x37b73bfc,0x3b022bd9,
0xbbbcba1f,0xb4143927,0x2bd9ba3f,0xbbfcb900,0x3887b593,0xba99bb80,0x3b5a3ad0,0x364eb832,0x38b03c00,0x3a7ca248,0xb97232a1,0x39dc3bd4,0xbbafb534,0x34753b91,0xb75ebbed,0xbb1ab04e,
0x38873bfc,0x3a992bd9,0xb5f13807,0x3b6e3ae9,0xbb80b4d5,0x35933ba0,0xba7cbbaf,0xb8b03475,0xaf0ebad0,0xbbf4b832,0x3a1fa8b6,0xb927bbff,0x3bed39ba,0x304eb996,0x37053bd4,0x3b3032a1,
0x2f0eb972,0xbbf4b9dc,0x3927b115,0xba1fbbe6,0x3bbc3a99,0x3414b887,0x394d3c00,0x39fea248,0xb64e3705,0x3b5a3b30,0xbab5b04e,0x385d3bed,0xbad0bba0,0xb83234d5,0xb6aabbaf,0xbb46b475,
0xb9dca248,0x39723c00,0xbad0b2a1,0x38323bd4,0xb927bbfc,0xba1fabd9,0xb7b7bbbc,0xbb02b414,0x3a5e2f0e,0xb8d8bbf4,0x3b3034d5,0xb705bba0,0x38873be6,0x3a993115,0x364e3b80,0x3b5a3593,
0x3bff3996,0xa8b6b9ba,0x3bc9385d,0xb365bab5,0x2d7e39fe,0x3bf8394d,0x34753ae9,0x3baf3807,0xbbedb900,0x304e3a3f,0xbb91b75e,0x35343b1a,0xb1dbba7c,0xbbddb8b0,0xb5f1bb46,0xbb6eb6aa,
0xba3fbbff,0xb90028b6,0xbbf8ba7c,0xad7e38b0,0x3807b1db,0xbae9bbdd,0xabd9b996,0xbbfcb9ba,0x3b6e3b91,0x35f1b534,0x3bd438d8,0xb2a1ba5e,0xb365375e,0x3bc93b1a,0x35933b02,0x3b8037b7,
0x31db39fe,0x3bdd394d,0x3b5a3bbc,0x364eb414,0xbb46b75e,0x36aa3b1a,0xb11537b7,0x3be63b02,0xb900bbc9,0xba3fb365,0xbbf8b9dc,0x2d7e3972,0x38d8a248,0xba5ebc00,0xb534bab5,0xbb91b85d,
0x3807ad7e,0xbae9bbf8,0xb9febbf4,0xb94daf0e,0x3bdd3b46,0x31dbb6aa,0x35f1b365,0xbb6ebbc9,0x31153996,0x3be639ba,0x3bff3ab5,0x28b6b85d,0xbb02b705,0x37b73b30,0x34d53a5e,0x3ba038d8,
0xbb91b900,0x35343a3f,0x38073b1a,0x3ae9375e,0xb996bbc9,0xb9bab365,0xb887a8b6,0x3a993bff,0x3593b2a1,0xbb80bbd4,0xbbe6bb5a,0xb115364e,0x3bf83a5e,0xad7eb8d8,0xb475b9fe,0xbbafb94d,
0x3b6e3bed,0x35f1b04e,0xb2a1b94d,0xbbd4b9fe,0x31153900,0x3be63a3f,0x39dc34d5,0xb972bba0,0xba1fb593,0x39273b80,0x3baf3bc9,0x3475b365,0xbb91bbdd,0xb53431db,0x34143996,0x3bbc39ba,
0xb75eba7c,0xbb1ab8b0,0xaf0e3593,0x3bf43b80,0x3705a248,0xbb30bc00,0xbae9b85d,0x38073ab5,0x3bdd3a5e,0xb1dbb8d8,0xbb5abbfc,0xb64e2bd9,0x39dc3baf,0x39723475,0xb365b927,0xbbc9ba1f,
0xb36531db,0x3bc93bdd,0x36aa2248,0xbb46bc00,0xbb02b8d8,0x37b73a5e,0x3ba039fe,0xb4d5b94d,0xbb91bbf8,0xb5342d7e,0x3ae93bf4,0x38072f0e,0xb64eb9dc,0xbb5ab972,0x32a138b0,0x3bd43a7c,
0x3a7c385d,0xb8b0bab5,0xb972b5f1,0x39dc3b6e,0x3bf43bbc,0x2f0eb414,0xbbf8bb30,0x2d7e3705,0x394d3b1a,0x39fe375e,0xba5ebbaf,0xb8d8b475,0xa2483593,0x3c003b80,0xb1dbb832,0xbbddbad0,
0xbbf8bbc9,0xad7e3365,0x3b023972,0xb7b7b9dc,0xb9febb5a,0xb94db64e,0x3bed3bdd,0x304eb1db,0xb2a1b807,0xbbd4bae9,0x39ba3b30,0x39963705,0x36aa2f0e,0xbb46bbf4,0x3115375e,0x3be63b1a,
0x39963ae9,0x39ba3807,0xbbddbb30,0x31db3705,0x336537b7,0x3bc93b02,0xbb80bbf8,0xb593ad7e,0xb4d5a8b6,0x3ba03bff,0xb900ba7c,0xba3fb8b0,0xb9feb85d,0x394d3ab5,0xb04eb64e,0xbbedbb5a,
0xabd9b475,0xbbfcbbaf,0x3bed3bf8,0x304ead7e,0x35f13115,0xbb6ebbe6,0x3ab53b80,0x385d3593,0x39dc3887,0xb972ba99,0x38323996,0x3ad039ba,0x3ba03ae9,0xb4d5b807,0x2f0e3534,0x3bf43b91,
0xb8d8b75e,0x3a5e3b1a,0xbb30bbaf,0xb705b475,0xbab5b9dc,0x385d3972,0xb996ba7c,0xb9bab8b0,0xbbc9bb5a,0x3365364e,0xb6aab887,0xbb46ba99,0xbbf4bbfc,0xaf0e2bd9,0xad7eb414,0xbbf8bbbc,
0x3bd43b91,0xb2a1b534,0x39ba3a5e,0x399638d8,0x3bff3bf8,0x28b6ad7e,0x38323900,0x3ad03a3f,0x3baf3be6,0x34753115,0x34d536aa,0x3ba03b46,0x3ae93b5a,0x3807364e,0x2bd931db,0x3bfc3bdd,
0xbb02bb46,0xb7b7b6aa,0xb75eb832,0xbb1abad0,0xba5ebab5,0xb8d8b85d,0xb534b64e,0xbb91bb5a,0xb996b9fe,0xb9bab94d,0xb1dbb414,0xbbddbbbc,0xb8b0b927,0xba7cba1f,0xa8b6af0e,0xbbffbbf4,
0x359335f1,0x3b803b6e,0x311531db,0x3be63bdd,0x34d53534,0x3ba03b91,0x2f0e304e,0x3bf43bed,0x34143475,0x3bbc3baf,0x2bd92d7e,0x3bfc3bf8,0x32a13365,0x3bd43bc9,0x224828b6,0x3c003bff,
0x40000,0x60002,0xc0008,0xe000a,0x380034,0x3a0036,0x40003c,0x42003e,0x6c0068,0x6e006a,0x740070,0x760072,0xa0009c,0xa2009e,0xa800a4,0xaa00a6,
0xd400d0,0xd600d2,0xdc00d8,0xde00da,0x1080104,0x10a0106,0x110010c,0x112010e,0x13c0138,0x13e013a,0x1440140,0x1460142,0x170016c,0x172016e,0x1780174,0x17a0176,
0x1a401a0,0x1a601a2,0x1ac01a8,0x1ae01aa,0x1d801d4,0x1da01d6,0x1e001dc,0x1e201de,0x20c0208,0x20e020a,0x2140210,0x2160212,0x240023c,0x242023e,0x2480244,0x24a0246,
0x2740270,0x2760272,0x27c0278,0x27e027a,0x2a802a4,0x2aa02a6,0x2b002ac,0x2b202ae,0x2dc02d8,0x2de02da,0x2e402e0,0x2e602e2,0x310030c,0x312030e,0x3180314,0x31a0316,
0x3440340,0x3460342,0x34c0348,0x34e034a,0x3780374,0x37a0376,0x380037c,0x382037e,0x3ac03a8,0x3ae03aa,0x3b403b0,0x3b603b2,0x3e003dc,0x3e203de,0x3e803e4,0x3ea03e6,
0x4140410,0x4160412,0x41c0418,0x41e041a,0x4480444,0x44a0446,0x450044c,0x452044e,0x47c0478,0x47e047a,0x4840480,0x4860482,0x4b004ac,0x4b204ae,0x4b804b4,0x4ba04b6,
0x4e404e0,0x4e604e2,0x4ec04e8,0x4ee04ea,0x5180514,0x51a0516,0x520051c,0x522051e,0x54c0548,0x54e054a,0x5540550,0x5560552,0x580057c,0x582057e,0x5880584,0x58a0586,
0x5b405b0,0x5b605b2,0x5bc05b8,0x5be05ba,0x5e805e4,0x5ea05e6,0x5f005ec,0x5f205ee,0x61c0618,0x61e061a,0x6240620,0x6260622,0x650064c,0x652064e,0x6580654,0x65a0656,
0x140010,0x160012,0x120010,0x440012,0x480044,0x4a0046,0x460044,0x780046,0x7c0078,0x7e007a,0x7a0078,0xac007a,0xb000ac,0xb200ae,0xae00ac,0xe000ae,
0xe400e0,0xe600e2,0xe200e0,0x11400e2,0x1180114,0x11a0116,0x1160114,0x1480116,0x14c0148,0x14e014a,0x14a0148,0x17c014a,0x180017c,0x182017e,0x17e017c,0x1b0017e,
0x1b401b0,0x1b601b2,0x1b201b0,0x1e401b2,0x1e801e4,0x1ea01e6,0x1e601e4,0x21801e6,0x21c0218,0x21e021a,0x21a0218,0x24c021a,0x250024c,0x252024e,0x24e024c,0x280024e,
0x2840280,0x2860282,0x2820280,0x2b40282,0x2b802b4,0x2ba02b6,0x2b602b4,0x2e802b6,0x2ec02e8,0x2ee02ea,0x2ea02e8,0x31c02ea,0x320031c,0x322031e,0x31e031c,0x350031e,
0x3540350,0x3560352,0x3520350,0x3840352,0x3880384,0x38a0386,0x3860384,0x3b80386,0x3bc03b8,0x3be03ba,0x3ba03b8,0x3ec03ba,0x3f003ec,0x3f203ee,0x3ee03ec,0x42003ee,
0x4240420,0x4260422,0x4220420,0x4540422,0x4580454,0x45a0456,0x4560454,0x4880456,0x48c0488,0x48e048a,0x48a0488,0x4bc048a,0x4c004bc,0x4c204be,0x4be04bc,0x4f004be,
0x4f404f0,0x4f604f2,0x4f204f0,0x52404f2,0x5280524,0x52a0526,0x5260524,0x5580526,0x55c0558,0x55e055a,0x55a0558,0x58c055a,0x590058c,0x592058e,0x58e058c,0x5c0058e,
0x5c405c0,0x5c605c2,0x5c205c0,0x5f405c2,0x5f805f4,0x5fa05f6,0x5f605f4,0x62805f6,0x62c0628,0x62e062a,0x62a0628,0x65c062a,0x660065c,0x662065e,0x65e065c,0x18065e,
0x180018,0x4c001a,0x1a0018,0x4c001a,0x4c004c,0x80004e,0x4e004c,0x80004e,0x800080,0xb40082,0x820080,0xb40082,0xb400b4,0xe800b6,0xb600b4,0xe800b6,
0xe800e8,0x11c00ea,0xea00e8,0x11c00ea,0x11c011c,0x150011e,0x11e011c,0x150011e,0x1500150,0x1840152,0x1520150,0x1840152,0x1840184,0x1b80186,0x1860184,0x1b80186,
0x1b801b8,0x1ec01ba,0x1ba01b8,0x1ec01ba,0x1ec01ec,0x22001ee,0x1ee01ec,0x22001ee,0x2200220,0x2540222,0x2220220,0x2540222,0x2540254,0x2880256,0x2560254,0x2880256,
0x2880288,0x2bc028a,0x28a0288,0x2bc028a,0x2bc02bc,0x2f002be,0x2be02bc,0x2f002be,0x2f002f0,0x32402f2,0x2f202f0,0x32402f2,0x3240324,0x3580326,0x3260324,0x3580326,
0x3580358,0x38c035a,0x35a0358,0x38c035a,0x38c038c,0x3c0038e,0x38e038c,0x3c0038e,0x3c003c0,0x3f403c2,0x3c203c0,0x3f403c2,0x3f403f4,0x42803f6,0x3f603f4,0x42803f6,
0x4280428,0x45c042a,0x42a0428,0x45c042a,0x45c045c,0x490045e,0x45e045c,0x490045e,0x4900490,0x4c40492,0x4920490,0x4c40492,0x4c404c4,0x4f804c6,0x4c604c4,0x4f804c6,
0x4f804f8,0x52c04fa,0x4fa04f8,0x52c04fa,0x52c052c,0x560052e,0x52e052c,0x560052e,0x5600560,0x5940562,0x5620560,0x5940562,0x5940594,0x5c80596,0x5960594,0x5c80596,
0x5c805c8,0x5fc05ca,0x5ca05c8,0x5fc05ca,0x5fc05fc,0x63005fe,0x5fe05fc,0x63005fe,0x6300630,0x6640632,0x6320630,0x6640632,0x6640664,0x1c0666,0x6660664,0x1c0666,
0x1c001c,0x50001e,0x1e001c,0x50001e,0x500050,0x840052,0x520050,0x840052,0x840084,0xb80086,0x860084,0xb80086,0xb800b8,0xec00ba,0xba00b8,0xec00ba,
0xec00ec,0x12000ee,0xee00ec,0x12000ee,0x1200120,0x1540122,0x1220120,0x1540122,0x1540154,0x1880156,0x1560154,0x1880156,0x1880188,0x1bc018a,0x18a0188,0x1bc018a,
0x1bc01bc,0x1f001be,0x1be01bc,0x1f001be,0x1f001f0,0x22401f2,0x1f201f0,0x22401f2,0x2240224,0x2580226,0x2260224,0x2580226,0x2580258,0x28c025a,0x25a0258,0x28c025a,
0x28c028c,0x2c0028e,0x28e028c,0x2c0028e,0x2c002c0,0x2f402c2,0x2c202c0,0x2f402c2,0x2f402f4,0x32802f6,0x2f602f4,0x32802f6,0x3280328,0x35c032a,0x32a0328,0x35c032a,
0x35c035c,0x390035e,0x35e035c,0x390035e,0x3900390,0x3c40392,0x3920390,0x3c40392,0x3c403c4,0x3f803c6,0x3c603c4,0x3f803c6,0x3f803f8,0x42c03fa,0x3fa03f8,0x42c03fa,
0x42c042c,0x460042e,0x42e042c,0x460042e,0x4600460,0x4940462,0x4620460,0x4940462,0x4940494,0x4c80496,0x4960494,0x4c80496,0x4c804c8,0x4fc04ca,0x4ca04c8,0x4fc04ca,
0x4fc04fc,0x53004fe,0x4fe04fc,0x53004fe,0x5300530,0x5640532,0x5320530,0x5640532,0x5640564,0x5980566,0x5660564,0x5980566,0x5980598,0x5cc059a,0x59a0598,0x5cc059a,
0x5cc05cc,0x60005ce,0x5ce05cc,0x60005ce,0x6000600,0x6340602,0x6020600,0x6340602,0x6340634,0x6680636,0x6360634,0x6680636,0x6680668,0x20066a,0x66a0668,0x20066a,
0x5d605d6,0x60a05d6,0x5d605d6,0x60a060a,0x60a060a,0x63e063e,0x60a060a,0x63e063e,0x63e063e,0x672063e,0x63e063e,0x6720672,0x6720672,0x280028,0x6720672,0x280028,
0x5060506,0x53a0506,0x5060506,0x53a053a,0x53a053a,0x56e056e,0x53a053a,0x56e056e,0x56e056e,0x5a2056e,0x56e056e,0x5a205a2,0x5a205a2,0x5d605d6,0x5a205a2,0x5d605d6,
0x4360436,0x46a0436,0x4360436,0x46a046a,0x46a046a,0x49e049e,0x46a046a,0x49e049e,0x49e049e,0x4d2049e,0x49e049e,0x4d204d2,0x4d204d2,0x5060506,0x4d204d2,0x5060506,
0x3660366,0x39a0366,0x3660366,0x39a039a,0x39a039a,0x3ce03ce,0x39a039a,0x3ce03ce,0x3ce03ce,0x40203ce,0x3ce03ce,0x4020402,0x4020402,0x4360436,0x4020402,0x4360436,
0x2960296,0x2ca0296,0x2960296,0x2ca02ca,0x2ca02ca,0x2fe02fe,0x2ca02ca,0x2fe02fe,0x2fe02fe,0x33202fe,0x2fe02fe,0x3320332,0x3320332,0x3660366,0x3320332,0x3660366,
0x1c601c6,0x1fa01c6,0x1c601c6,0x1fa01fa,0x1fa01fa,0x22e022e,0x1fa01fa,0x22e022e,0x22e022e,0x262022e,0x22e022e,0x2620262,0x2620262,0x2960296,0x2620262,0x2960296,
0xf600f6,0x12a00f6,0xf600f6,0x12a012a,0x12a012a,0x15e015e,0x12a012a,0x15e015e,0x15e015e,0x192015e,0x15e015e,0x1920192,0x1920192,0x1c601c6,0x1920192,0x1c601c6,
0x260026,0x5a0026,0x260026,0x5a005a,0x5a005a,0x8e008e,0x5a005a,0x8e008e,0x8e008e,0xc2008e,0x8e008e,0xc200c2,0xc200c2,0xf600f6,0xc200c2,0xf600f6,
0x5d405d4,0x60805d4,0x5d405d4,0x6080608,0x6080608,0x63c063c,0x6080608,0x63c063c,0x63c063c,0x670063c,0x63c063c,0x6700670,0x6700670,0x260026,0x6700670,0x260026,
0x5040504,0x5380504,0x5040504,0x5380538,0x5380538,0x56c056c,0x5380538,0x56c056c,0x56c056c,0x5a0056c,0x56c056c,0x5a005a0,0x5a005a0,0x5d405d4,0x5a005a0,0x5d405d4,
0x4340434,0x4680434,0x4340434,0x4680468,0x4680468,0x49c049c,0x4680468,0x49c049c,0x49c049c,0x4d0049c,0x49c049c,0x4d004d0,0x4d004d0,0x5040504,0x4d004d0,0x5040504,
0x3640364,0x3980364,0x3640364,0x3980398,0x3980398,0x3cc03cc,0x3980398,0x3cc03cc,0x3cc03cc,0x40003cc,0x3cc03cc,0x4000400,0x4000400,0x4340434,0x4000400,0x4340434,
0x2940294,0x2c80294,0x2940294,0x2c802c8,0x2c802c8,0x2fc02fc,0x2c802c8,0x2fc02fc,0x2fc02fc,0x33002fc,0x2fc02fc,0x3300330,0x3300330,0x3640364,0x3300330,0x3640364,
0x1c401c4,0x1f801c4,0x1c401c4,0x1f801f8,0x1f801f8,0x22c022c,0x1f801f8,0x22c022c,0x22c022c,0x260022c,0x22c022c,0x2600260,0x2600260,0x2940294,0x2600260,0x2940294,
0xf400f4,0x12800f4,0xf400f4,0x1280128,0x1280128,0x15c015c,0x1280128,0x15c015c,0x15c015c,0x190015c,0x15c015c,0x1900190,0x1900190,0x1c401c4,0x1900190,0x1c401c4,
0x240024,0x580024,0x240024,0x580058,0x580058,0x8c008c,0x580058,0x8c008c,0x8c008c,0xc0008c,0x8c008c,0xc000c0,0xc000c0,0xf400f4,0xc000c0,0xf400f4,
0x5d205d2,0x60605d2,0x5d205d2,0x6060606,0x6060606,0x63a063a,0x6060606,0x63a063a,0x63a063a,0x66e063a,0x63a063a,0x66e066e,0x66e066e,0x240024,0x66e066e,0x240024,
0x5020502,0x5360502,0x5020502,0x5360536,0x5360536,0x56a056a,0x5360536,0x56a056a,0x56a056a,0x59e056a,0x56a056a,0x59e059e,0x59e059e,0x5d205d2,0x59e059e,0x5d205d2,
0x4320432,0x4660432,0x4320432,0x4660466,0x4660466,0x49a049a,0x4660466,0x49a049a,0x49a049a,0x4ce049a,0x49a049a,0x4ce04ce,0x4ce04ce,0x5020502,0x4ce04ce,0x5020502,
0x3620362,0x3960362,0x3620362,0x3960396,0x3960396,0x3ca03ca,0x3960396,0x3ca03ca,0x3ca03ca,0x3fe03ca,0x3ca03ca,0x3fe03fe,0x3fe03fe,0x4320432,0x3fe03fe,0x4320432,
0x2920292,0x2c60292,0x2920292,0x2c602c6,0x2c602c6,0x2fa02fa,0x2c602c6,0x2fa02fa,0x2fa02fa,0x32e02fa,0x2fa02fa,0x32e032e,0x32e032e,0x3620362,0x32e032e,0x3620362,
0x1c201c2,0x1f601c2,0x1c201c2,0x1f601f6,0x1f601f6,0x22a022a,0x1f601f6,0x22a022a,0x22a022a,0x25e022a,0x22a022a,0x25e025e,0x25e025e,0x2920292,0x25e025e,0x2920292,
0xf200f2,0x12600f2,0xf200f2,0x1260126,0x1260126,0x15a015a,0x1260126,0x15a015a,0x15a015a,0x18e015a,0x15a015a,0x18e018e,0x18e018e,0x1c201c2,0x18e018e,0x1c201c2,
0x220022,0x560022,0x220022,0x560056,0x560056,0x8a008a,0x560056,0x8a008a,0x8a008a,0xbe008a,0x8a008a,0xbe00be,0xbe00be,0xf200f2,0xbe00be,0xf200f2,
0x5d005d0,0x60405d0,0x5d005d0,0x6040604,0x6040604,0x6380638,0x6040604,0x6380638,0x6380638,0x66c0638,0x6380638,0x66c066c,0x66c066c,0x220022,0x66c066c,0x220022,
0x5000500,0x5340500,0x5000500,0x5340534,0x5340534,0x5680568,0x5340534,0x5680568,0x5680568,0x59c0568,0x5680568,0x59c059c,0x59c059c,0x5d005d0,0x59c059c,0x5d005d0,
0x4300430,0x4640430,0x4300430,0x4640464,0x4640464,0x4980498,0x4640464,0x4980498,0x4980498,0x4cc0498,0x4980498,0x4cc04cc,0x4cc04cc,0x5000500,0x4cc04cc,0x5000500,
0x3600360,0x3940360,0x3600360,0x3940394,0x3940394,0x3c803c8,0x3940394,0x3c803c8,0x3c803c8,0x3fc03c8,0x3c803c8,0x3fc03fc,0x3fc03fc,0x4300430,0x3fc03fc,0x4300430,
0x2900290,0x2c40290,0x2900290,0x2c402c4,0x2c402c4,0x2f802f8,0x2c402c4,0x2f802f8,0x2f802f8,0x32c02f8,0x2f802f8,0x32c032c,0x32c032c,0x3600360,0x32c032c,0x3600360,
0x1c001c0,0x1f401c0,0x1c001c0,0x1f401f4,0x1f401f4,0x2280228,0x1f401f4,0x2280228,0x2280228,0x25c0228,0x2280228,0x25c025c,0x25c025c,0x2900290,0x25c025c,0x2900290,
0xf000f0,0x12400f0,0xf000f0,0x1240124,0x1240124,0x1580158,0x1240124,0x1580158,0x1580158,0x18c0158,0x1580158,0x18c018c,0x18c018c,0x1c001c0,0x18c018c,0x1c001c0,
0x200020,0x540020,0x200020,0x540054,0x540054,0x880088,0x540054,0x880088,0x880088,0xbc0088,0x880088,0xbc00bc,0xbc00bc,0xf000f0,0xbc00bc,0xf000f0,
0x30003000,0x30003000,0x30003000,0x30003000,0x30003000,0x30003000,0x30003000,0x30003000,0x0,0x0,0x0,0x0,0x0,0x0,0x0,0x0,
0x30003000,0x30003000,0x30003000,0x30003000,0x30003000,0x30003000,0x30003000,0x30003000,0x0,0x0,0x0,0x0,0x0,0x0,0x0,0x0,
0x2a1f2da8,0xaf64ada8,0xaa1fada8,0x2f642da8,0x2f643000,0xaa1f0000,0xaf64b000,0x2a1f8000,0x2f642da8,0x2a1f2da8,0xaf64ada8,0xaa1fada8,0x2a1f0000,0x2f643000,0xaa1f0000,0xaf64b000,
0x263e2c72,0xafd9aea7,0xa63eac72,0x2fd92ea7,0x2ea72fd9,0xac72a63e,0xaea7afd9,0x2c72263e,0x2fd92ea7,0x263e2c72,0xafd9aea7,0xa63eac72,0x2c72263e,0x2ea72fd9,0xac72a63e,0xaea7afd9,
0x2da80000,0xada80000,0x2da88000,0xada80000,0x2da83000,0xada8b000,0x2da83000,0xada8b000,0x2da83000,0xada8b000,0x2da83000,0xada8b000,0xada80000,0x2da88000,0xada80000,0x2da88000,
0x2f642a1f,0xaf64aa1f,0x2f642a1f,0xaf64aa1f,0x2a1f2f64,0xaa1faf64,0x2a1f2f64,0xaa1faf64,0x2a1f2f64,0xaa1faf64,0x2a1f2f64,0xaa1faf64,0xaf64aa1f,0x2f642a1f,0xaf64aa1f,0x2f642a1f,
0xaa1f2da8,0x2f642da8,0x2a1fada8,0xaf64ada8,0x2f640000,0xaa1fb000,0xaf640000,0x2a1f3000,0xaf64ada8,0xaa1f2da8,0x2f642da8,0x2a1fada8,0x2a1f3000,0x2f648000,0xaa1fb000,0xaf640000,
0xaea7263e,0x2c722fd9,0x2ea7a63e,0xac72afd9,0x2fd92c72,0x263eaea7,0xafd9ac72,0xa63e2ea7,0xac72afd9,0xaea7263e,0x2c722fd9,0x2ea7a63e,0xa63e2ea7,0x2fd92c72,0x263eaea7,0xafd9ac72,
0xada82da8,0xada82da8,0xada82da8,0xada82da8,0x2da8ada8,0x2da8ada8,0x2da8ada8,0x2da8ada8,0x2da82da8,0x2da82da8,0x2da82da8,0x2da82da8,0xada8ada8,0xada8ada8,0xada8ada8,0xada8ada8,
0x3000,0x3000,0x3000,0x80003000,0x8000b000,0x8000b000,0x8000b000,0x8000b000,0x30000000,0x30008000,0x30008000,0x30008000,0xb0000000,0xb0000000,0xb0000000,0xb0000000,
0x2ea7263e,0xac722fd9,0xaea7a63e,0x2c72afd9,0xafd92c72,0xa63eaea7,0x2fd9ac72,0x263e2ea7,0x2c72afd9,0x2ea7263e,0xac722fd9,0xaea7a63e,0x263e2ea7,0xafd92c72,0xa63eaea7,0x2fd9ac72,
0x2f64ada8,0x2a1f2da8,0xaf642da8,0xaa1fada8,0xaa1f3000,0xaf640000,0x2a1fb000,0x2f648000,0xaa1fada8,0x2f64ada8,0x2a1f2da8,0xaf642da8,0x2f640000,0xaa1f3000,0xaf640000,0x2a1fb000,
0xaa1f2f64,0x2a1faf64,0xaa1f2f64,0x2a1faf64,0x2f64aa1f,0xaf642a1f,0x2f64aa1f,0xaf642a1f,0xaf642a1f,0x2f64aa1f,0xaf642a1f,0x2f64aa1f,0xaa1f2f64,0x2a1faf64,0xaa1f2f64,0x2a1faf64,
0x2da80000,0xada80000,0x2da88000,0xada80000,0x2da8b000,0xada83000,0x2da8b000,0xada83000,0xada83000,0x2da8b000,0xada83000,0x2da8b000,0x2da88000,0xada80000,0x2da88000,0xada88000,
0xa63e2c72,0x2fd9aea7,0x263eac72,0xafd92ea7,0xaea72fd9,0x2c72a63e,0x2ea7afd9,0xac72263e,0xafd92ea7,0xa63e2c72,0x2fd9aea7,0x263eac72,0xac72263e,0xaea72fd9,0x2c72a63e,0x2ea7afd9,
0x2f64ada8,0x2a1fada8,0xaf642da8,0xaa1f2da8,0x2a1f0000,0x2f64b000,0xaa1f0000,0xaf643000,0xaa1f2da8,0x2f64ada8,0x2a1fada8,0xaf642da8,0xaf643000,0x2a1f8000,0x2f64b000,0xaa1f8000,
0xb0003000,0xb0003000,0xb0003000,0xb0003000,0xb0003000,0xb0003000,0xb0003000,0xb0003000,0x0,0x8000,0x8000,0x80008000,0x8000,0x8000,0x8000,0x8000,
0x80000000,0x80000000,0x80008000,0x80008000,0x80000000,0x80008000,0x80008000,0x80008000,0xb0003000,0xb0003000,0xb0003000,0xb0003000,0xb0003000,0xb0003000,0xb0003000,0xb0003000,
0xaa1f2da8,0x2f64ada8,0x2a1fada8,0xaf642da8,0xaf643000,0x2a1f0000,0x2f64b000,0xaa1f8000,0xaf642da8,0xaa1f2da8,0x2f64ada8,0x2a1fada8,0xaa1f0000,0xaf643000,0x2a1f0000,0x2f64b000,
0x2fd9aea7,0x263eac72,0xafd92ea7,0xa63e2c72,0x2c72a63e,0x2ea7afd9,0xac72263e,0xaea72fd9,0xa63e2c72,0x2fd9aea7,0x263eac72,0xafd92ea7,0xaea72fd9,0x2c72a63e,0x2ea7afd9,0xac72263e,
0xada80000,0x2da80000,0xada88000,0x2da80000,0xada83000,0x2da8b000,0xada83000,0x2da8b000,0xada83000,0x2da8b000,0xada83000,0x2da8b000,0x2da80000,0xada88000,0x2da88000,0xada88000,
0xaa1f2f64,0x2a1faf64,0xaa1f2f64,0x2a1faf64,0x2f64aa1f,0xaf642a1f,0x2f64aa1f,0xaf642a1f,0x2f64aa1f,0xaf642a1f,0x2f64aa1f,0xaf642a1f,0x2a1faf64,0xaa1f2f64,0x2a1faf64,0xaa1f2f64,
0x2a1f2da8,0xaf642da8,0xaa1fada8,0x2f64ada8,0xaf640000,0x2a1fb000,0x2f640000,0xaa1f3000,0x2f64ada8,0x2a1f2da8,0xaf642da8,0xaa1fada8,0xaa1f3000,0xaf648000,0x2a1fb000,0x2f640000,
0x2c72afd9,0x2ea7263e,0xac722fd9,0xaea7a63e,0x263e2ea7,0xafd92c72,0xa63eaea7,0x2fd9ac72,0xaea7a63e,0x2c72afd9,0x2ea7263e,0xac722fd9,0x2fd9ac72,0x263e2ea7,0xafd92c72,0xa63eaea7,
0x2da8ada8,0x2da8ada8,0x2da8ada8,0x2da8ada8,0xada82da8,0xada82da8,0xada82da8,0xada82da8,0x2da82da8,0x2da82da8,0x2da82da8,0x2da82da8,0xada8ada8,0xada8ada8,0xada8ada8,0xada8ada8,
0x80003000,0x80003000,0x80003000,0x3000,0xb000,0x8000b000,0xb000,0xb000,0xb0000000,0xb0008000,0xb0008000,0xb0008000,0x30000000,0x30000000,0x30000000,0x30008000,
0x2c722fd9,0x2ea7a63e,0xac72afd9,0xaea7263e,0x263eaea7,0xafd9ac72,0xa63e2ea7,0x2fd92c72,0xaea7263e,0x2c722fd9,0x2ea7a63e,0xac72afd9,0x2fd92c72,0x263eaea7,0xafd9ac72,0xa63e2ea7,
0xaf64ada8,0xaa1f2da8,0x2f642da8,0x2a1fada8,0x2a1f3000,0x2f648000,0xaa1fb000,0xaf648000,0x2a1fada8,0xaf64ada8,0xaa1f2da8,0x2f642da8,0xaf640000,0x2a1f3000,0x2f648000,0xaa1fb000,
0x2f642a1f,0xaf64aa1f,0x2f642a1f,0xaf64aa1f,0x2a1f2f64,0xaa1faf64,0x2a1f2f64,0xaa1faf64,0xaa1faf64,0x2a1f2f64,0xaa1faf64,0x2a1f2f64,0x2f642a1f,0xaf64aa1f,0x2f642a1f,0xaf64aa1f,
0xada80000,0x2da80000,0xada88000,0x2da88000,0xada8b000,0x2da83000,0xada8b000,0x2da83000,0x2da83000,0xada8b000,0x2da83000,0xada8b000,0xada88000,0x2da88000,0xada88000,0x2da80000,
0x2fd92ea7,0x263e2c72,0xafd9aea7,0xa63eac72,0x2c72263e,0x2ea72fd9,0xac72a63e,0xaea7afd9,0xa63eac72,0x2fd92ea7,0x263e2c72,0xafd9aea7,0xaea7afd9,0x2c72263e,0x2ea72fd9,0xac72a63e,
0xaf64ada8,0xaa1fada8,0x2f642da8,0x2a1f2da8,0xaa1f0000,0xaf64b000,0x2a1f0000,0x2f643000,0x2a1f2da8,0xaf64ada8,0xaa1fada8,0x2f642da8,0x2f643000,0xaa1f8000,0xaf64b000,0x2a1f0000,
0x80008000,0x80008000,0x80008000,0x80008000,0x80008000,0x80008000,0x80008000,0x80008000,0x30003000,0x30003000,0x30003000,0x30003000,0x30003000,0x30003000,0x30003000,0x30003000,
0x80008000,0x80008000,0x80008000,0x80008000,0x80008000,0x80008000,0x80008000,0x80008000,0x30003000,0x30003000,0x30003000,0x30003000,0x30003000,0x30003000,0x30003000,0x30003000,
0xaf64ada8,0xaa1fada8,0x2f642da8,0x2a1f2da8,0xaa1f8000,0xaf64b000,0x2a1f8000,0x2f643000,0x2a1f2da8,0xaf64ada8,0xaa1fada8,0x2f642da8,0x2f643000,0xaa1f0000,0xaf64b000,0x2a1f8000,
0xafd9aea7,0xa63eac72,0x2fd92ea7,0x263e2c72,0xac72a63e,0xaea7afd9,0x2c72263e,0x2ea72fd9,0x263e2c72,0xafd9aea7,0xa63eac72,0x2fd92ea7,0x2ea72fd9,0xac72a63e,0xaea7afd9,0x2c72263e,
0x2da83000,0xada8b000,0x2da83000,0xada8b000,0xada80000,0x2da88000,0xada80000,0x2da88000,0xada88000,0x2da88000,0xada80000,0x2da88000,0xada8b000,0x2da83000,0xada8b000,0x2da83000,
0x2a1f2f64,0xaa1faf64,0x2a1f2f64,0xaa1faf64,0xaf64aa1f,0x2f642a1f,0xaf64aa1f,0x2f642a1f,0xaf64aa1f,0x2f642a1f,0xaf64aa1f,0x2f642a1f,0xaa1faf64,0x2a1f2f64,0xaa1faf64,0x2a1f2f64,
0xaf64ada8,0xaa1f2da8,0x2f642da8,0x2a1fada8,0x2a1f3000,0x2f648000,0xaa1fb000,0xaf640000,0x2a1fada8,0xaf64ada8,0xaa1f2da8,0x2f642da8,0xaf648000,0x2a1f3000,0x2f648000,0xaa1fb000,
0xac72afd9,0xaea7263e,0x2c722fd9,0x2ea7a63e,0xa63e2ea7,0x2fd92c72,0x263eaea7,0xafd9ac72,0x2ea7a63e,0xac72afd9,0xaea7263e,0x2c722fd9,0xafd9ac72,0xa63e2ea7,0x2fd92c72,0x263eaea7,
0xada8ada8,0xada8ada8,0xada8ada8,0xada8ada8,0x2da82da8,0x2da82da8,0x2da82da8,0x2da82da8,0xada82da8,0xada82da8,0xada82da8,0xada82da8,0x2da8ada8,0x2da8ada8,0x2da8ada8,0x2da8ada8,
0xb0008000,0xb0000000,0xb0000000,0xb0000000,0x30008000,0x30008000,0x30008000,0x30008000,0x3000,0x3000,0x3000,0x80003000,0x8000b000,0x8000b000,0x8000b000,0x8000b000,
0xac722fd9,0xaea7a63e,0x2c72afd9,0x2ea7263e,0xa63eaea7,0x2fd9ac72,0x263e2ea7,0xafd92c72,0x2ea7263e,0xac722fd9,0xaea7a63e,0x2c72afd9,0xafd92c72,0xa63eaea7,0x2fd9ac72,0x263e2ea7,
0x2a1f2da8,0xaf642da8,0xaa1fada8,0x2f64ada8,0xaf648000,0x2a1fb000,0x2f648000,0xaa1f3000,0x2f64ada8,0x2a1f2da8,0xaf642da8,0xaa1fada8,0xaa1f3000,0xaf640000,0x2a1fb000,0x2f648000,
0xaf642a1f,0x2f64aa1f,0xaf642a1f,0x2f64aa1f,0xaa1f2f64,0x2a1faf64,0xaa1f2f64,0x2a1faf64,0x2a1faf64,0xaa1f2f64,0x2a1faf64,0xaa1f2f64,0xaf642a1f,0x2f64aa1f,0xaf642a1f,0x2f64aa1f,
0xada83000,0x2da8b000,0xada83000,0x2da8b000,0x2da88000,0xada80000,0x2da88000,0xada88000,0xada88000,0x2da88000,0xada80000,0x2da88000,0xada83000,0x2da8b000,0xada83000,0x2da8b000,
0xafd92ea7,0xa63e2c72,0x2fd9aea7,0x263eac72,0xac72263e,0xaea72fd9,0x2c72a63e,0x2ea7afd9,0x263eac72,0xafd92ea7,0xa63e2c72,0x2fd9aea7,0x2ea7afd9,0xac72263e,0xaea72fd9,0x2c72a63e,
0xaa1f2da8,0x2f64ada8,0x2a1fada8,0xaf642da8,0xaf643000,0x2a1f8000,0x2f64b000,0xaa1f8000,0xaf642da8,0xaa1f2da8,0x2f64ada8,0x2a1fada8,0xaa1f8000,0xaf643000,0x2a1f8000,0x2f64b000,
0x80008000,0x80000000,0x80000000,0x0,0x80000000,0x80000000,0x80000000,0x80000000,0xb0003000,0xb0003000,0xb0003000,0xb0003000,0xb0003000,0xb0003000,0xb0003000,0xb0003000,
0x3000b000,0x3000b000,0x3000b000,0x3000b000,0x3000b000,0x3000b000,0x3000b000,0x3000b000,0x80000000,0x80000000,0x80008000,0x80008000,0x80000000,0x80008000,0x80008000,0x80008000,
0x2f64ada8,0x2a1fada8,0xaf642da8,0xaa1f2da8,0x2a1f8000,0x2f64b000,0xaa1f8000,0xaf643000,0xaa1f2da8,0x2f64ada8,0x2a1fada8,0xaf642da8,0xaf643000,0x2a1f0000,0x2f64b000,0xaa1f8000,
0x263eac72,0xafd92ea7,0xa63e2c72,0x2fd9aea7,0x2ea7afd9,0xac72263e,0xaea72fd9,0x2c72a63e,0x2fd9aea7,0x263eac72,0xafd92ea7,0xa63e2c72,0x2c72a63e,0x2ea7afd9,0xac72263e,0xaea72fd9,
0xada83000,0x2da8b000,0xada83000,0x2da8b000,0x2da80000,0xada88000,0x2da88000,0xada88000,0x2da88000,0xada88000,0x2da80000,0xada88000,0x2da8b000,0xada83000,0x2da8b000,0xada83000,
0x2f64aa1f,0xaf642a1f,0x2f64aa1f,0xaf642a1f,0x2a1faf64,0xaa1f2f64,0x2a1faf64,0xaa1f2f64,0x2a1faf64,0xaa1f2f64,0x2a1faf64,0xaa1f2f64,0xaf642a1f,0x2f64aa1f,0xaf642a1f,0x2f64aa1f,
0x2f64ada8,0x2a1f2da8,0xaf642da8,0xaa1fada8,0xaa1f3000,0xaf648000,0x2a1fb000,0x2f640000,0xaa1fada8,0x2f64ada8,0x2a1f2da8,0xaf642da8,0x2f648000,0xaa1f3000,0xaf648000,0x2a1fb000,
0xaea7a63e,0x2c72afd9,0x2ea7263e,0xac722fd9,0x2fd9ac72,0x263e2ea7,0xafd92c72,0xa63eaea7,0xac722fd9,0xaea7a63e,0x2c72afd9,0x2ea7263e,0xa63eaea7,0x2fd9ac72,0x263e2ea7,0xafd92c72,
0xada8ada8,0xada8ada8,0xada8ada8,0xada8ada8,0x2da82da8,0x2da82da8,0x2da82da8,0x2da82da8,0x2da8ada8,0x2da8ada8,0x2da8ada8,0x2da8ada8,0xada82da8,0xada82da8,0xada82da8,0xada82da8,
0x30008000,0x30000000,0x30000000,0x30000000,0xb0008000,0xb0008000,0xb0008000,0xb0000000,0x80003000,0x80003000,0x80003000,0x3000,0xb000,0x8000b000,0xb000,0xb000,
0x2ea7a63e,0xac72afd9,0xaea7263e,0x2c722fd9,0xafd9ac72,0xa63e2ea7,0x2fd92c72,0x263eaea7,0x2c722fd9,0x2ea7a63e,0xac72afd9,0xaea7263e,0x263eaea7,0xafd9ac72,0xa63e2ea7,0x2fd92c72,
0xaa1f2da8,0x2f642da8,0x2a1fada8,0xaf64ada8,0x2f648000,0xaa1fb000,0xaf640000,0x2a1f3000,0xaf64ada8,0xaa1f2da8,0x2f642da8,0x2a1fada8,0x2a1f3000,0x2f648000,0xaa1fb000,0xaf648000,
0xaa1faf64,0x2a1f2f64,0xaa1faf64,0x2a1f2f64,0x2f642a1f,0xaf64aa1f,0x2f642a1f,0xaf64aa1f,0xaf64aa1f,0x2f642a1f,0xaf64aa1f,0x2f642a1f,0xaa1faf64,0x2a1f2f64,0xaa1faf64,0x2a1f2f64,
0x2da83000,0xada8b000,0x2da83000,0xada8b000,0xada88000,0x2da88000,0xada88000,0x2da80000,0x2da88000,0xada88000,0x2da80000,0xada80000,0x2da83000,0xada8b000,0x2da83000,0xada8b000,
0xa63eac72,0x2fd92ea7,0x263e2c72,0xafd9aea7,0xaea7afd9,0x2c72263e,0x2ea72fd9,0xac72a63e,0xafd9aea7,0xa63eac72,0x2fd92ea7,0x263e2c72,0xac72a63e,0xaea7afd9,0x2c72263e,0x2ea72fd9,
0x2a1f2da8,0xaf64ada8,0xaa1fada8,0x2f642da8,0x2f643000,0xaa1f8000,0xaf64b000,0x2a1f0000,0x2f642da8,0x2a1f2da8,0xaf64ada8,0xaa1fada8,0x2a1f8000,0x2f643000,0xaa1f8000,0xaf64b000,
0x3c003c00,0x3c003c00,0x3c003c00,0x3c003c00,0x3c003c00,0x3c003c00,0x3c003c00,0x3c003c00,0x80008000,0x80008000,0x80008000,0x80008000,0x80008000,0x80008000,0x80008000,0x80008000,
0x3bd93c00,0x3aa73b64,0x387239a8,0x323e361f,0xb23e0000,0xb872b61f,0xbaa7b9a8,0xbbd9bb64,0xb23e8000,0xb872b61f,0xbaa7b9a8,0xbbd9bb64,0xbbd9bc00,0xbaa7bb64,0xb872b9a8,0xb23eb61f,
0xbb64bc00,0xb61fb9a8,0x361f8000,0x3b6439a8,0x3b643c00,0x361f39a8,0xb61f0000,0xbb64b9a8,0x361f8000,0x3b6439a8,0x3b643c00,0x361f39a8,0xb61f8000,0xbb64b9a8,0xbb64bc00,0xb61fb9a8,
0x38728000,0x3bd93b64,0x323e39a8,0xbaa7b61f,0x3aa73c00,0xb23e361f,0xbbd9b9a8,0xb872bb64,0x3aa73c00,0xb23e361f,0xbbd9b9a8,0xb872bb64,0xb8728000,0xbbd9bb64,0xb23eb9a8,0x3aa7361f,
0xbc008000,0x3c008000,0xbc000000,0x3c008000,0xbc000000,0x3c008000,0xbc000000,0x3c008000,0x3c00,0x8000bc00,0x3c00,0x8000bc00,0x3c00,0x8000bc00,0x80003c00,0x8000bc00,
0xbbd98000,0x3aa7361f,0xb872b9a8,0x323e3b64,0x323ebc00,0xb8723b64,0x3aa7b9a8,0xbbd9361f,0xb23e3c00,0x3872bb64,0xbaa739a8,0x3bd9b61f,0xbbd90000,0x3aa7361f,0xb872b9a8,0x323e3b64,
0x3b648000,0xb61fb9a8,0xb61f3c00,0x3b64b9a8,0xbb648000,0x361f39a8,0x361fbc00,0xbb6439a8,0x361fbc00,0xbb6439a8,0x3b648000,0xb61fb9a8,0xb61f3c00,0x3b64b9a8,0xbb640000,0x361f39a8,
0xb8723c00,0x3bd9b61f,0xb23eb9a8,0xbaa73b64,0xbaa78000,0xb23e3b64,0x3bd9b9a8,0xb872b61f,0x3aa78000,0x323ebb64,0xbbd939a8,0x3872361f,0xb8723c00,0x3bd9b61f,0xb23eb9a8,0xbaa73b64,
0xbbd93c00,0xbaa73b64,0xb87239a8,0xb23e361f,0x323e8000,0x3872b61f,0x3aa7b9a8,0x3bd9bb64,0x323e8000,0x3872b61f,0x3aa7b9a8,0x3bd9bb64,0x3bd9bc00,0x3aa7bb64,0x3872b9a8,0x323eb61f,
0xbc003c00,0xbc003c00,0xbc003c00,0xbc003c00,0xbc003c00,0xbc003c00,0xbc003c00,0xbc003c00,0x80008000,0x80000000,0x80000000,0x80000000,0x80000000,0x80000000,0x0,0x80000000,
0xb8728000,0xbbd93b64,0xb23e39a8,0x3aa7b61f,0xbaa73c00,0x323e361f,0x3bd9b9a8,0x3872bb64,0xbaa73c00,0x323e361f,0x3bd9b9a8,0x3872bb64,0x38728000,0x3bd9bb64,0x323eb9a8,0xbaa7361f,
0x3b64bc00,0x361fb9a8,0xb61f8000,0xbb6439a8,0xbb643c00,0xb61f39a8,0x361f0000,0x3b64b9a8,0xb61f8000,0xbb6439a8,0xbb643c00,0xb61f39a8,0x361f8000,0x3b64b9a8,0x3b64bc00,0x361fb9a8,
0x3bd98000,0xbaa7361f,0x3872b9a8,0xb23e3b64,0xb23ebc00,0x38723b64,0xbaa7b9a8,0x3bd9361f,0x323e3c00,0xb872bb64,0x3aa739a8,0xbbd9b61f,0x3bd98000,0xbaa7361f,0x3872b9a8,0xb23e3b64,
0x3c008000,0xbc008000,0x3c000000,0xbc008000,0x3c000000,0xbc008000,0x3c000000,0xbc000000,0x80003c00,0xbc00,0x80003c00,0x8000bc00,0x80003c00,0xbc00,0x80003c00,0xbc00,
0x38723c00,0xbbd9b61f,0x323eb9a8,0x3aa73b64,0x3aa78000,0x323e3b64,0xbbd9b9a8,0x3872b61f,0xbaa78000,0xb23ebb64,0x3bd939a8,0xb872361f,0x38723c00,0xbbd9b61f,0x323eb9a8,0x3aa73b64,
0xbb640000,0x361fb9a8,0x361f3c00,0xbb64b9a8,0x3b648000,0xb61f39a8,0xb61fbc00,0x3b6439a8,0xb61fbc00,0x3b6439a8,0xbb640000,0x361fb9a8,0x361f3c00,0xbb64b9a8,0x3b648000,0xb61f39a8,
0x39a83c00,0xb9a80000,0xb9a8bc00,0x39a88000,0x39a83c00,0xb9a80000,0xb9a8bc00,0x39a88000,0xb9a88000,0xb9a8bc00,0x39a88000,0x39a83c00,0xb9a80000,0xb9a8bc00,0x39a88000,0x39a83c00,
0x38723c00,0xbbd9b61f,0x323eb9a8,0x3aa73b64,0xbaa70000,0xb23ebb64,0x3bd939a8,0xb872361f,0xbaa78000,0xb23ebb64,0x3bd939a8,0xb872361f,0xb872bc00,0x3bd9361f,0xb23e39a8,0xbaa7bb64,
0xb61fbc00,0x3b6439a8,0xbb640000,0x361fb9a8,0x361f3c00,0xbb64b9a8,0x3b648000,0xb61f39a8,0x3b648000,0xb61f39a8,0xb61fbc00,0x3b6439a8,0xbb648000,0x361fb9a8,0x361f3c00,0xbb64b9a8,
0x3bd98000,0xbaa7361f,0x3872b9a8,0xb23e3b64,0x323e3c00,0xb872bb64,0x3aa739a8,0xbbd9b61f,0x323e3c00,0xb872bb64,0x3aa739a8,0xbbd9b61f,0xbbd98000,0x3aa7b61f,0xb87239a8,0x323ebb64,
0xb9a88000,0xb9a83c00,0x39a88000,0x39a8bc00,0xb9a80000,0xb9a83c00,0x39a88000,0x39a8bc00,0xb9a83c00,0x39a88000,0x39a8bc00,0xb9a80000,0xb9a83c00,0x39a88000,0x39a8bc00,0xb9a88000,
0xb8728000,0xbbd93b64,0xb23e39a8,0x3aa7b61f,0x3aa7bc00,0xb23eb61f,0xbbd939a8,0xb8723b64,0xbaa73c00,0x323e361f,0x3bd9b9a8,0x3872bb64,0xb8728000,0xbbd93b64,0xb23e39a8,0x3aa7b61f,
0x361f8000,0x3b64b9a8,0x3b64bc00,0x361fb9a8,0xb61f8000,0xbb6439a8,0xbb643c00,0xb61f39a8,0x3b64bc00,0x361fb9a8,0xb61f8000,0xbb6439a8,0xbb643c00,0xb61f39a8,0x361f8000,0x3b64b9a8,
0xbbd93c00,0xbaa73b64,0xb87239a8,0xb23e361f,0xb23e8000,0xb872361f,0xbaa739a8,0xbbd93b64,0x323e8000,0x3872b61f,0x3aa7b9a8,0x3bd9bb64,0xbbd93c00,0xbaa73b64,0xb87239a8,0xb23e361f,
0xb8723c00,0x3bd9b61f,0xb23eb9a8,0xbaa73b64,0x3aa78000,0x323ebb64,0xbbd939a8,0x3872361f,0x3aa78000,0x323ebb64,0xbbd939a8,0x3872361f,0x3872bc00,0xbbd9361f,0x323e39a8,0x3aa7bb64,
0xb9a83c00,0x39a80000,0x39a8bc00,0xb9a88000,0xb9a83c00,0x39a88000,0x39a8bc00,0xb9a88000,0x39a88000,0x39a8bc00,0xb9a88000,0xb9a83c00,0x39a80000,0x39a8bc00,0xb9a88000,0xb9a83c00,
0xbbd98000,0x3aa7361f,0xb872b9a8,0x323e3b64,0xb23e3c00,0x3872bb64,0xbaa739a8,0x3bd9b61f,0xb23e3c00,0x3872bb64,0xbaa739a8,0x3bd9b61f,0x3bd98000,0xbaa7b61f,0x387239a8,0xb23ebb64,
0x361fbc00,0xbb6439a8,0x3b640000,0xb61fb9a8,0xb61f3c00,0x3b64b9a8,0xbb648000,0x361f39a8,0xbb648000,0x361f39a8,0x361fbc00,0xbb6439a8,0x3b648000,0xb61fb9a8,0xb61f3c00,0x3b64b9a8,
0x38728000,0x3bd93b64,0x323e39a8,0xbaa7b61f,0xbaa7bc00,0x323eb61f,0x3bd939a8,0x38723b64,0x3aa73c00,0xb23e361f,0xbbd9b9a8,0xb872bb64,0x38728000,0x3bd93b64,0x323e39a8,0xbaa7b61f,
0x39a88000,0x39a83c00,0xb9a88000,0xb9a8bc00,0x39a80000,0x39a83c00,0xb9a80000,0xb9a8bc00,0x39a83c00,0xb9a88000,0xb9a8bc00,0x39a88000,0x39a83c00,0xb9a88000,0xb9a8bc00,0x39a80000,
0x3bd93c00,0x3aa73b64,0x387239a8,0x323e361f,0x323e8000,0x3872361f,0x3aa739a8,0x3bd93b64,0xb23e8000,0xb872b61f,0xbaa7b9a8,0xbbd9bb64,0x3bd93c00,0x3aa73b64,0x387239a8,0x323e361f,
0xb61f8000,0xbb64b9a8,0xbb64bc00,0xb61fb9a8,0x361f8000,0x3b6439a8,0x3b643c00,0x361f39a8,0xbb64bc00,0xb61fb9a8,0x361f0000,0x3b6439a8,0x3b643c00,0x361f39a8,0xb61f8000,0xbb64b9a8,
0x0,0x0,0x0,0x0,0x0,0x0,0x0,0x0,0x3c003c00,0x3c003c00,0x3c003c00,0x3c003c00,0x3c003c00,0x3c003c00,0x3c003c00,0x3c003c00,
0x323e0000,0x3872361f,0x3aa739a8,0x3bd93b64,0x3bd93c00,0x3aa73b64,0x387239a8,0x323e361f,0x3bd93c00,0x3aa73b64,0x387239a8,0x323e361f,0xb23e0000,0xb872b61f,0xbaa7b9a8,0xbbd9bb64,
0xb61f0000,0xbb64b9a8,0xbb64bc00,0xb61fb9a8,0x361f0000,0x3b6439a8,0x3b643c00,0x361f39a8,0xbb64bc00,0xb61fb9a8,0x361f8000,0x3b6439a8,0x3b643c00,0x361f39a8,0xb61f0000,0xbb64b9a8,
0xbaa7bc00,0x323eb61f,0x3bd939a8,0x38723b64,0x38720000,0x3bd93b64,0x323e39a8,0xbaa7b61f,0x38728000,0x3bd93b64,0x323e39a8,0xbaa7b61f,0x3aa73c00,0xb23e361f,0xbbd9b9a8,0xb872bb64,
0x3c00,0x8000bc00,0x3c00,0x8000bc00,0x3c00,0x8000bc00,0x80003c00,0x8000bc00,0x3c000000,0xbc000000,0x3c008000,0xbc000000,0x3c008000,0xbc000000,0x3c008000,0xbc000000,
0xb23e3c00,0x3872bb64,0xbaa739a8,0x3bd9b61f,0xbbd90000,0x3aa7361f,0xb872b9a8,0x323e3b64,0x3bd90000,0xbaa7b61f,0x387239a8,0xb23ebb64,0xb23e3c00,0x3872bb64,0xbaa739a8,0x3bd9b61f,
0x361fbc00,0xbb6439a8,0x3b648000,0xb61fb9a8,0xb61f3c00,0x3b64b9a8,0xbb640000,0x361f39a8,0xbb640000,0x361f39a8,0x361fbc00,0xbb6439a8,0x3b640000,0xb61fb9a8,0xb61f3c00,0x3b64b9a8,
0x3aa78000,0x323ebb64,0xbbd939a8,0x3872361f,0xb8723c00,0x3bd9b61f,0xb23eb9a8,0xbaa73b64,0x3872bc00,0xbbd9361f,0x323e39a8,0x3aa7bb64,0x3aa70000,0x323ebb64,0xbbd939a8,0x3872361f,
0xb23e0000,0xb872361f,0xbaa739a8,0xbbd93b64,0xbbd93c00,0xbaa73b64,0xb87239a8,0xb23e361f,0xbbd93c00,0xbaa73b64,0xb87239a8,0xb23e361f,0x323e8000,0x3872b61f,0x3aa7b9a8,0x3bd9bb64,
0x0,0x8000,0x8000,0x8000,0x8000,0x8000,0x80008000,0x8000,0xbc003c00,0xbc003c00,0xbc003c00,0xbc003c00,0xbc003c00,0xbc003c00,0xbc003c00,0xbc003c00,
0x3aa7bc00,0xb23eb61f,0xbbd939a8,0xb8723b64,0xb8720000,0xbbd93b64,0xb23e39a8,0x3aa7b61f,0xb8728000,0xbbd93b64,0xb23e39a8,0x3aa7b61f,0xbaa73c00,0x323e361f,0x3bd9b9a8,0x3872bb64,
0x361f0000,0x3b64b9a8,0x3b64bc00,0x361fb9a8,0xb61f0000,0xbb6439a8,0xbb643c00,0xb61f39a8,0x3b64bc00,0x361fb9a8,0xb61f8000,0xbb6439a8,0xbb643c00,0xb61f39a8,0x361f0000,0x3b64b9a8,
0x323e3c00,0xb872bb64,0x3aa739a8,0xbbd9b61f,0x3bd98000,0xbaa7361f,0x3872b9a8,0xb23e3b64,0xbbd90000,0x3aa7b61f,0xb87239a8,0x323ebb64,0x323e3c00,0xb872bb64,0x3aa739a8,0xbbd9b61f,
0x80003c00,0xbc00,0x80003c00,0x8000bc00,0x80003c00,0xbc00,0x80003c00,0xbc00,0xbc000000,0x3c000000,0xbc008000,0x3c000000,0xbc008000,0x3c000000,0xbc008000,0x3c008000,
0xbaa78000,0xb23ebb64,0x3bd939a8,0xb872361f,0x38723c00,0xbbd9b61f,0x323eb9a8,0x3aa73b64,0xb872bc00,0x3bd9361f,0xb23e39a8,0xbaa7bb64,0xbaa70000,0xb23ebb64,0x3bd939a8,0xb872361f,
0xb61fbc00,0x3b6439a8,0xbb640000,0x361fb9a8,0x361f3c00,0xbb64b9a8,0x3b648000,0xb61f39a8,0x3b648000,0xb61f39a8,0xb61fbc00,0x3b6439a8,0xbb640000,0x361fb9a8,0x361f3c00,0xbb64b9a8,
0x39a80000,0x39a83c00,0xb9a80000,0xb9a8bc00,0x39a88000,0x39a83c00,0xb9a80000,0xb9a8bc00,0x39a83c00,0xb9a80000,0xb9a8bc00,0x39a88000,0x39a83c00,0xb9a80000,0xb9a8bc00,0x39a88000,
0x3aa70000,0x323e3b64,0xbbd9b9a8,0x3872b61f,0x38723c00,0xbbd9b61f,0x323eb9a8,0x3aa73b64,0x38723c00,0xbbd9b61f,0x323eb9a8,0x3aa73b64,0xbaa70000,0xb23ebb64,0x3bd939a8,0xb872361f,
0xbb640000,0x361fb9a8,0x361f3c00,0xbb64b9a8,0x3b640000,0xb61f39a8,0xb61fbc00,0x3b6439a8,0xb61fbc00,0x3b6439a8,0xbb640000,0x361fb9a8,0x361f3c00,0xbb64b9a8,0x3b648000,0xb61f39a8,
0xb23ebc00,0x38723b64,0xbaa7b9a8,0x3bd9361f,0x3bd90000,0xbaa7361f,0x3872b9a8,0xb23e3b64,0x3bd98000,0xbaa7361f,0x3872b9a8,0xb23e3b64,0x323e3c00,0xb872bb64,0x3aa739a8,0xbbd9b61f,
0xb9a83c00,0x39a88000,0x39a8bc00,0xb9a80000,0xb9a83c00,0x39a88000,0x39a8bc00,0xb9a88000,0x39a80000,0x39a8bc00,0xb9a80000,0xb9a83c00,0x39a88000,0x39a8bc00,0xb9a80000,0xb9a83c00,
0xbaa73c00,0x323e361f,0x3bd9b9a8,0x3872bb64,0xb8728000,0xbbd93b64,0xb23e39a8,0x3aa7b61f,0x38720000,0x3bd9bb64,0x323eb9a8,0xbaa7361f,0xbaa73c00,0x323e361f,0x3bd9b9a8,0x3872bb64,
0x3b64bc00,0x361fb9a8,0xb61f8000,0xbb6439a8,0xbb643c00,0xb61f39a8,0x361f8000,0x3b64b9a8,0xb61f0000,0xbb6439a8,0xbb643c00,0xb61f39a8,0x361f0000,0x3b64b9a8,0x3b64bc00,0x361fb9a8,
0x323e8000,0x3872b61f,0x3aa7b9a8,0x3bd9bb64,0xbbd93c00,0xbaa73b64,0xb87239a8,0xb23e361f,0x3bd9bc00,0x3aa7bb64,0x3872b9a8,0x323eb61f,0x323e0000,0x3872b61f,0x3aa7b9a8,0x3bd9bb64,
0xbaa70000,0xb23e3b64,0x3bd9b9a8,0xb872b61f,0xb8723c00,0x3bd9b61f,0xb23eb9a8,0xbaa73b64,0xb8723c00,0x3bd9b61f,0xb23eb9a8,0xbaa73b64,0x3aa78000,0x323ebb64,0xbbd939a8,0x3872361f,
0xb9a80000,0xb9a83c00,0x39a80000,0x39a8bc00,0xb9a88000,0xb9a83c00,0x39a80000,0x39a8bc00,0xb9a83c00,0x39a80000,0x39a8bc00,0xb9a88000,0xb9a83c00,0x39a88000,0x39a8bc00,0xb9a88000,
0x323ebc00,0xb8723b64,0x3aa7b9a8,0xbbd9361f,0xbbd90000,0x3aa7361f,0xb872b9a8,0x323e3b64,0xbbd98000,0x3aa7361f,0xb872b9a8,0x323e3b64,0xb23e3c00,0x3872bb64,0xbaa739a8,0x3bd9b61f,
0x3b640000,0xb61fb9a8,0xb61f3c00,0x3b64b9a8,0xbb640000,0x361f39a8,0x361fbc00,0xbb6439a8,0x361fbc00,0xbb6439a8,0x3b640000,0xb61fb9a8,0xb61f3c00,0x3b64b9a8,0xbb648000,0x361f39a8,
0x3aa73c00,0xb23e361f,0xbbd9b9a8,0xb872bb64,0x38728000,0x3bd93b64,0x323e39a8,0xbaa7b61f,0xb8720000,0xbbd9bb64,0xb23eb9a8,0x3aa7361f,0x3aa73c00,0xb23e361f,0xbbd9b9a8,0xb872bb64,
0x39a83c00,0xb9a88000,0xb9a8bc00,0x39a88000,0x39a83c00,0xb9a88000,0xb9a8bc00,0x39a80000,0xb9a80000,0xb9a8bc00,0x39a80000,0x39a83c00,0xb9a88000,0xb9a8bc00,0x39a88000,0x39a83c00,
0xb23e8000,0xb872b61f,0xbaa7b9a8,0xbbd9bb64,0x3bd93c00,0x3aa73b64,0x387239a8,0x323e361f,0xbbd9bc00,0xbaa7bb64,0xb872b9a8,0xb23eb61f,0xb23e0000,0xb872b61f,0xbaa7b9a8,0xbbd9bb64,
0xbb64bc00,0xb61fb9a8,0x361f0000,0x3b6439a8,0x3b643c00,0x361f39a8,0xb61f8000,0xbb64b9a8,0x361f0000,0x3b6439a8,0x3b643c00,0x361f39a8,0xb61f0000,0xbb64b9a8,0xbb64bc00,0xb61fb9a8,
};
__device__ __align__(1024) bf16 g_x1T[DM * XP];
__device__ __align__(1024) bf16 g_x2T[DM * XP];
__device__ __align__(1024) uint4 g_of[8][16][1280];
__device__ __align__(1024) float g_fs[2][SEQ];

#define TS_SMEM 0
#define TS_DECL
#define TS_ARG
#define TS_PASS
#define TS_PHASE(p)
#define TS(i)
#define TSX(row, i)
#define TS_BEGIN
#define TS_END

struct cplx { float r, i; };
__device__ __forceinline__ cplx cmul(cplx a, cplx b) {
    cplx o;
    o.r = fmaf(a.r, b.r, -a.i * b.i);
    o.i = fmaf(a.r, b.i, a.i * b.r);
    return o;
}
__device__ __forceinline__ cplx csq(cplx a) {
    cplx o;
    o.r = fmaf(a.r, a.r, -a.i * a.i);
    o.i = 2.f * a.r * a.i;
    return o;
}
__device__ __forceinline__ cplx cexp_p(float arl, float ai, float p) {
    float mag = ex2(arl * p);
    float ang = ai * p;
    float n = rintf(ang * 0.15915494309189535f);
    float r = fmaf(n, -6.2831854820251465f, ang);
    r = fmaf(n, 1.7484555e-7f, r);
    cplx o;
    o.r = mag * __cosf(r);
    o.i = mag * __sinf(r);
    return o;
}

__device__ __forceinline__ uint32_t pack2h(float lo, float hi) {
    uint32_t r;
    asm("cvt.rn.f16x2.f32 %0, %1, %2;" : "=r"(r) : "f"(hi), "f"(lo));
    return r;
}
__device__ __forceinline__ uint32_t hmul(uint32_t a, uint32_t b) { uint32_t d; asm("mul.rn.f16x2 %0, %1, %2;" : "=r"(d) : "r"(a), "r"(b)); return d; }
__device__ __forceinline__ uint32_t hfma(uint32_t a, uint32_t b, uint32_t c) { uint32_t d; asm("fma.rn.f16x2 %0, %1, %2, %3;" : "=r"(d) : "r"(a), "r"(b), "r"(c)); return d; }
__device__ __forceinline__ uint32_t hfms(uint32_t a, uint32_t b, uint32_t c) {
    uint32_t d;
    asm("{\n.reg .b32 n;\nneg.f16x2 n, %1;\nfma.rn.f16x2 %0, n, %2, %3;\n}" : "=r"(d) : "r"(a), "r"(b), "r"(c));
    return d;
}
__device__ __forceinline__ uint32_t hadd(uint32_t a, uint32_t b) { uint32_t d; asm("add.rn.f16x2 %0, %1, %2;" : "=r"(d) : "r"(a), "r"(b)); return d; }
__device__ __forceinline__ uint32_t hsub(uint32_t a, uint32_t b) { uint32_t d; asm("sub.rn.f16x2 %0, %1, %2;" : "=r"(d) : "r"(a), "r"(b)); return d; }
__device__ __forceinline__ uint4 ldg_tab(int tab, int t) { return ldg128((const uint4*)c_fft + t + tab * 128); }
__device__ __forceinline__ uint32_t u4(const uint4& v, int i) { return i == 0 ? v.x : i == 1 ? v.y : i == 2 ? v.z : v.w; }
struct cpair { uint32_t r, i; };
__device__ __forceinline__ cpair pmul(cpair p, uint32_t z) {
    const __half2 zv = *reinterpret_cast<const __half2*>(&z), pr = *reinterpret_cast<const __half2*>(&p.r), pi = *reinterpret_cast<const __half2*>(&p.i);
    const __half2 zr = __low2half2(zv), zi = __high2half2(zv);
    const __half2 a = __hfma2(__hneg2(pi), zi, __hmul2(pr, zr)), b = __hfma2(pi, zr, __hmul2(pr, zi));
    return {*reinterpret_cast<const uint32_t*>(&a), *reinterpret_cast<const uint32_t*>(&b)};
}
__device__ __forceinline__ uint32_t packz(cplx z) { return pack2h(z.r, z.i); }
__device__ __forceinline__ void wgmma_kg(float (&d)[24], uint64_t da, uint64_t db, int scale_d) {
    asm volatile("{\n.reg .pred p;\nsetp.ne.b32 p, %26, 0;\n"
                 "wgmma.mma_async.sync.aligned.m64n48k16.f32.f16.f16 "
                 "{%0,%1,%2,%3,%4,%5,%6,%7,%8,%9,%10,%11,%12,%13,%14,%15,%16,%17,%18,%19,%20,%21,%22,%23}, %24, %25, p, 1, 1, 1, 1;\n}\n"
                 : "+f"(d[0]), "+f"(d[1]), "+f"(d[2]), "+f"(d[3]), "+f"(d[4]), "+f"(d[5]), "+f"(d[6]), "+f"(d[7]), "+f"(d[8]), "+f"(d[9]),
                   "+f"(d[10]), "+f"(d[11]), "+f"(d[12]), "+f"(d[13]), "+f"(d[14]), "+f"(d[15]), "+f"(d[16]), "+f"(d[17]), "+f"(d[18]), "+f"(d[19]),
                   "+f"(d[20]), "+f"(d[21]), "+f"(d[22]), "+f"(d[23])
                 : "l"(da), "l"(db), "r"(scale_d));
}

struct SsmParams { const bf16 *lar, *aim, *cre, *cim, *logdt, *dskip; const unsigned* epoch; };
constexpr int KG_TABLES = 6 * 16384, KG_RES = 1664;
struct KgShared { uint32_t kmax[6], kexp[6]; float cinv[6], tap0[6]; };
#define KS(f, i) (ks + (uint32_t)offsetof(KgShared, f) + 4 * (i))
struct KgParams { uint32_t l[3], a[3], r[3], i[3], dt, ds; };

__device__ __forceinline__ bool kg_is_hi(int warp) { return ((warp >> 1) ^ (warp >> 2)) & 1; }
__device__ __forceinline__ void kgen_load(KgParams& kp, int d0, int warp, int lane, const SsmParams& sp) {
    const int d = d0 + min(2 * (warp >> 2) + (warp & 1), 4), idx = d * (NMODE / 2) + lane;
    const bf16 *pr = kg_is_hi(warp) ? sp.cre : sp.lar, *pi = kg_is_hi(warp) ? sp.cim : sp.aim;
    kp.dt = __ldg((const uint16_t*)sp.logdt + d);
#pragma unroll
    for (int j = 0; j < 3; j++) {
        kp.l[j] = __ldg((const uint32_t*)sp.lar + idx + 32 * j); kp.a[j] = __ldg((const uint32_t*)sp.aim + idx + 32 * j);
        kp.r[j] = __ldg((const uint32_t*)pr + idx + 32 * j); kp.i[j] = __ldg((const uint32_t*)pi + idx + 32 * j);
    }
    kp.ds = __ldg((const uint16_t*)sp.dskip + d0 + min(warp >> 1, 4));
}

struct KgAnchors { uint32_t v[8]; };
__device__ __forceinline__ KgAnchors kg_anchor_lo(const KgParams& kp, uint32_t sel, float dt) {
    auto B = [&](uint32_t v) { return __uint_as_float(__byte_perm(v, 0u, sel)); };
    const float arl = -rbf(ex2(B(kp.l[0]) * 1.4426950408889634f)) * dt * 1.4426950408889634f, ai = B(kp.a[0]) * dt;
    const cplx z8 = cexp_p(arl, ai, 8.f), z16 = csq(z8), z24 = cmul(z16, z8), z32 = csq(z16), z64 = csq(z32), z128 = csq(z64), z192 = cmul(z128, z64);
    return {{pack2h(1.f, z8.r), pack2h(0.f, z8.i), pack2h(z16.r, z24.r), pack2h(z16.i, z24.i), packz(z32), packz(z64), packz(z128), packz(z192)}};
}
__device__ __forceinline__ KgAnchors kg_anchor_hi(const KgParams& kp, uint32_t sel, float dt, float cs) {
    auto B = [&](uint32_t v) { return __uint_as_float(__byte_perm(v, 0u, sel)); };
    const float arl = -rbf(ex2(B(kp.l[0]) * 1.4426950408889634f)) * dt * 1.4426950408889634f, ai = B(kp.a[0]) * dt;
    const cplx z1 = cexp_p(arl, -ai, 1.f), z2 = csq(z1), z4 = csq(z2), z256 = cexp_p(arl, -ai, 256.f), z512 = csq(z256), z1024 = csq(z512);
    const cplx H0 = {B(kp.r[0]) * cs, -B(kp.i[0]) * cs}, H4 = cmul(H0, z4);
    return {{pack2h(H0.r, H4.r), pack2h(H0.i, H4.i), packz(z1), packz(z2), packz(z256), packz(z512), packz(z1024), 0u}};
}

template <class Idle>
__device__ __forceinline__ void kgen_tables(KgParams& kp, uint32_t scr, uint32_t dump, uint32_t ks, int warp, int lane, Idle idle TS_ARG) {
    const int wg = warp >> 2, half = warp & 1, sw = lane & 7;
    const bool hi = kg_is_hi(warp);
    TS(23);
    const float dt = rbf(ex2(bf_lo(kp.dt) * 1.4426950408889634f));
    uint32_t sel = (wg == 2 && half) ? 0x3244u : 0x1044u;
    float cs = 0.f;
    KgAnchors an;
    if (hi) {
        uint32_t m = 0;
#pragma unroll
        for (int j = 0; j < 3; j++) m = __vmaxu2(m, __vmaxu2(kp.r[j] & 0x7FFF7FFFu, kp.i[j] & 0x7FFF7FFFu));
        m = __reduce_max_sync(~0u, max(m << 16, m & 0xFFFF0000u));
        const uint32_t e = min(max(__float_as_uint(2.f * dt * __uint_as_float(m)) >> 23, 2u), 252u);
        cs = 2.f * dt * __uint_as_float((253u - e) << 23);
        if (lane == 0) { sts32(KS(cinv, 2 * wg + half), (e + 1u) << 23); sts32(KS(kmax, 2 * wg + half), 0u); }
        an = kg_anchor_hi(kp, sel, dt, cs);
    } else {
        an = kg_anchor_lo(kp, sel, dt);
    }
    float acc[24];
#pragma unroll
    for (int i = 0; i < 24; i++) acc[i] = 0.f;
    uint32_t tb = scr + 2 * wg * 16384 + lane * 128;
    uint64_t da = mkdesc(scr + 2 * wg * 16384, 4096, 1024, 1);
    int flip = 16384;
#pragma unroll 1
    for (int c = wg == 2 ? 1 : 0, step = wg == 2 ? 2 : 1; c < 6; c += step) {
        if (wg < 2) sel ^= 0x2200u;
        if (!hi) {
            if (c & 1) { kp.l[0] = kp.l[1]; kp.l[1] = kp.l[2]; kp.a[0] = kp.a[1]; kp.a[1] = kp.a[2]; }
            cpair p[4];
            p[0] = {an.v[0], an.v[1]}; p[1] = {an.v[2], an.v[3]};
            p[2] = pmul(p[0], an.v[4]); p[3] = pmul(p[1], an.v[4]);
#pragma unroll
            for (int j = 0; j < 4; j++) {
                cpair v[4];
#pragma unroll
                for (int i = 0; i < 4; i++) v[i] = j ? pmul(p[i], an.v[4 + j]) : p[i];
                const uint32_t a = tb + (((4 * half + j) ^ sw) << 4);
                sts128(a, make_uint4(v[0].r, v[1].r, v[2].r, v[3].r));
                sts128(a + 4096, make_uint4(v[0].i, v[1].i, v[2].i, v[3].i));
            }
            an = kg_anchor_lo(kp, sel, dt);
        } else {
            if (c & 1) {
#pragma unroll
                for (int j = 0; j < 2; j++) { kp.l[j] = kp.l[j + 1]; kp.a[j] = kp.a[j + 1]; kp.r[j] = kp.r[j + 1]; kp.i[j] = kp.i[j + 1]; }
            }
            const uint32_t h1 = an.v[2], h2 = an.v[3], h256 = an.v[4], h512 = an.v[5], h1024 = an.v[6];
            cpair p[11];
            p[0] = {an.v[0], an.v[1]};
            p[1] = pmul(p[0], h2); p[2] = pmul(p[0], h1); p[3] = pmul(p[1], h1);
            p[4] = pmul(p[0], h256); p[5] = pmul(p[1], h256); p[6] = pmul(p[0], h512); p[7] = pmul(p[4], h512);
            p[8] = pmul({__byte_perm(p[0].r, p[4].r, 0x5410), __byte_perm(p[0].i, p[4].i, 0x5410)}, h1024);
            p[9] = pmul(p[8], h512); p[10] = pmul(p[8], h1024);
#pragma unroll
            for (int j = 0; j < 3; j++) {
                const uint32_t a = tb + 8192 + (((3 * half + j) ^ sw) << 4);
                sts128(a, make_uint4(p[4 * j].r, p[4 * j + 1].r, p[4 * j + 2].r, p[j < 2 ? 4 * j + 3 : 10].r));
                sts128(a + 4096, make_uint4(p[4 * j].i, p[4 * j + 1].i, p[4 * j + 2].i, p[j < 2 ? 4 * j + 3 : 10].i));
            }
            an = kg_anchor_hi(kp, sel, dt, cs);
        }
        if (c == 0) TS(24);
        if (c == 3) TS(25);
        fence_async_smem();
        wg_wait<0>();
        named_bar(5 + wg, 128);
        wg_fence();
#pragma unroll
        for (int k = 0; k < 4; k++) wgmma_kg(acc, da + k * 128, da + 512 + k * 128, 1);
        wg_commit();
        tb += flip; da += flip >> 4; flip = -flip;
    }
    const bool up = warp & 2;
    const int r = 2 * wg + up, lo0 = 16 * half + (lane >> 2);
    const uint32_t o = dump + r * KG_RES + lo0 * 52 + 4 * (lane & 3);
    const float ci = __uint_as_float(lds32(KS(cinv, r)));
    const float ds = warp <= 8 ? bf_lo(kp.ds) : 0.f;
    TS(26);
    idle();
    wg_wait<0>();
    float v[12], m = 0.f;
#pragma unroll
    for (int j = 0; j < 12; j++) { v[j] = up ? acc[12 + j] : acc[j]; m = fmaxf(m, fabsf(v[j])); }
#pragma unroll
    for (int j = 0; j < 6; j++) sts32(o + (j & 1) * 416 + (j >> 1) * 16, pack2h(v[2 * j], v[2 * j + 1]));
    const uint32_t mm = __reduce_max_sync(~0u, __float_as_uint(m));
    if (lane == 0) {
        asm volatile("red.shared.max.u32 [%0], %1;" ::"r"(KS(kmax, r)), "r"(mm) : "memory");
        if (!half) sts32(KS(tap0, r), __float_as_uint(fmaf(ci, v[0], ds)));
    }
}
#define F_STAG 4
__device__ __forceinline__ void wgmma_h64_rs(uint32_t (&d)[16], const uint4& a, uint64_t db, int scale_d) {
    asm volatile("{\n.reg .pred p;\nsetp.ne.b32 p, %21, 0;\n"
                 "wgmma.mma_async.sync.aligned.m64n64k16.f16.f16.f16 {%0,%1,%2,%3,%4,%5,%6,%7,%8,%9,%10,%11,%12,%13,%14,%15}, {%16,%17,%18,%19}, %20, p, 1, 1, 1;\n}\n"
                 : "+r"(d[0]), "+r"(d[1]), "+r"(d[2]), "+r"(d[3]), "+r"(d[4]), "+r"(d[5]), "+r"(d[6]), "+r"(d[7]), "+r"(d[8]), "+r"(d[9]),
                   "+r"(d[10]), "+r"(d[11]), "+r"(d[12]), "+r"(d[13]), "+r"(d[14]), "+r"(d[15])
                 : "r"(a.x), "r"(a.y), "r"(a.z), "r"(a.w), "l"(db), "r"(scale_d));
}
template <int TB>
__device__ __forceinline__ void wgmma_h32_rs(uint32_t (&d)[8], const uint4& a, uint64_t db, int scale_d) {
    asm volatile("{\n.reg .pred p;\nsetp.ne.b32 p, %13, 0;\n"
                 "wgmma.mma_async.sync.aligned.m64n32k16.f16.f16.f16 {%0,%1,%2,%3,%4,%5,%6,%7}, {%8,%9,%10,%11}, %12, p, 1, 1, %14;\n}\n"
                 : "+r"(d[0]), "+r"(d[1]), "+r"(d[2]), "+r"(d[3]), "+r"(d[4]), "+r"(d[5]), "+r"(d[6]), "+r"(d[7])
                 : "r"(a.x), "r"(a.y), "r"(a.z), "r"(a.w), "l"(db), "r"(scale_d), "n"(TB));
}
__device__ __forceinline__ void wgmma_s1(uint32_t (&d)[16], const uint4& a, uint64_t db, int scale_d) { wgmma_h64_rs(d, a, db, scale_d); }
__device__ __forceinline__ void wgmma_s1(uint32_t (&d)[8], const uint4& a, uint64_t db, int scale_d) { wgmma_h32_rs<1>(d, a, db, scale_d); }
__device__ __forceinline__ void wgmma_s4(float (&d)[32], const uint4& a, uint64_t db, uint32_t meta, int scale_d) {
    asm volatile("{\n.reg .pred p;\nsetp.ne.b32 p, %38, 0;\n"
                 "wgmma.mma_async.sp.sync.aligned.m64n64k32.f32.f16.f16 {%0,%1,%2,%3,%4,%5,%6,%7,%8,%9,%10,%11,%12,%13,%14,%15,%16,%17,%18,%19,%20,%21,%22,%23,%24,%25,%26,%27,%28,%29,%30,%31}, {%32,%33,%34,%35}, %36, %37, 0, p, 1, 1, 1;\n}\n"
                 : "+f"(d[0]), "+f"(d[1]), "+f"(d[2]), "+f"(d[3]), "+f"(d[4]), "+f"(d[5]), "+f"(d[6]), "+f"(d[7]), "+f"(d[8]), "+f"(d[9]), "+f"(d[10]), "+f"(d[11]), "+f"(d[12]), "+f"(d[13]), "+f"(d[14]), "+f"(d[15]), "+f"(d[16]), "+f"(d[17]), "+f"(d[18]), "+f"(d[19]), "+f"(d[20]), "+f"(d[21]), "+f"(d[22]), "+f"(d[23]), "+f"(d[24]), "+f"(d[25]), "+f"(d[26]), "+f"(d[27]), "+f"(d[28]), "+f"(d[29]), "+f"(d[30]), "+f"(d[31])
                 : "r"(a.x), "r"(a.y), "r"(a.z), "r"(a.w), "l"(db), "r"(meta), "r"(scale_d));
}
__device__ __forceinline__ void wgmma_s4(float (&d)[16], const uint4& a, uint64_t db, uint32_t meta, int scale_d) {
    asm volatile("{\n.reg .pred p;\nsetp.ne.b32 p, %22, 0;\n"
                 "wgmma.mma_async.sp.sync.aligned.m64n32k32.f32.f16.f16 {%0,%1,%2,%3,%4,%5,%6,%7,%8,%9,%10,%11,%12,%13,%14,%15}, {%16,%17,%18,%19}, %20, %21, 0, p, 1, 1, 1;\n}\n"
                 : "+f"(d[0]), "+f"(d[1]), "+f"(d[2]), "+f"(d[3]), "+f"(d[4]), "+f"(d[5]), "+f"(d[6]), "+f"(d[7]), "+f"(d[8]), "+f"(d[9]), "+f"(d[10]), "+f"(d[11]), "+f"(d[12]), "+f"(d[13]), "+f"(d[14]), "+f"(d[15])
                 : "r"(a.x), "r"(a.y), "r"(a.z), "r"(a.w), "l"(db), "r"(meta), "r"(scale_d));
}

__device__ __forceinline__ uint32_t& u4r(uint4& v, int i) { return i == 0 ? v.x : i == 1 ? v.y : i == 2 ? v.z : v.w; }

template <int NC>
__device__ __forceinline__ void fft_stage(const uint32_t (&u)[2][4], int c, uint32_t eo, int w, int lane) {
    const int mi = lane >> 3, mj = lane & 7;
    const uint32_t a = eo + (8 * w + mj) * 128 + (((4 * c + mi) ^ mj) << 4);
    stsm_x4(a, hadd(u[0][0], u[1][0]), hadd(u[0][1], u[1][1]), hadd(u[0][2], u[1][2]), hadd(u[0][3], u[1][3]));
    stsm_x4(NC == 2 ? a + 4096 : a ^ 64, hsub(u[0][0], u[1][0]), hsub(u[0][1], u[1][1]), hsub(u[0][2], u[1][2]), hsub(u[0][3], u[1][3]));
}
template <int NC>
__device__ __forceinline__ void kernel_stage(const uint4 (&ko)[2], uint32_t kt, uint32_t ks, int r, uint32_t eo, int w, int lane) {
    uint32_t u[2][2][4], sc[NC], t0[NC];
#pragma unroll
    for (int c = 0; c < NC; c++) {
        auto L = [](uint32_t a) { return __uint_as_float(lds32(a)); };
        const float ci = L(KS(cinv, r + c)), k0 = L(KS(tap0, r + c)) + (NC == 1 ? L(KS(tap0, r + 1)) : 0.f);
        const float mx = fmaxf(ci * (L(KS(kmax, r + c)) + (NC == 1 ? L(KS(kmax, r + 1)) : 0.f) + 0x1p-14f), fabsf(k0));
        const uint32_t e = min(max(__float_as_uint(mx) >> 23, 4u), 250u);
        const float s = __uint_as_float((253u - e) << 23), f = s * ci;
        if (w == 0 && lane == 0) sts32(KS(kexp, r + c), e);
        sc[c] = pack2h(f, f); t0[c] = pack2h(k0 * s, 0.f);
    }
#pragma unroll
    for (int h = 0; h < 2; h++)
#pragma unroll
        for (int j = 0; j < 4; j++) {
            const uint32_t a0 = kt + (u4(ko[h], j) & 0xFFFF), a1 = kt + (u4(ko[h], j) >> 16);
#pragma unroll
            for (int c = 0; c < 2; c++)
                asm volatile("{\n.reg .b16 a, b;\nld.shared.b16 a, [%1];\nld.shared.b16 b, [%2];\nmov.b32 %0, {a, b};\n}"
                             : "=r"(u[c][h][j]) : "r"(a0 + c * KG_RES), "r"(a1 + c * KG_RES) : "memory");
            if (NC == 1) u[0][h][j] = hadd(u[0][h][j], u[1][h][j]);
#pragma unroll
            for (int c = 0; c < NC; c++) {
                u[c][h][j] = hmul(u[c][h][j], sc[c]);
                if (h + j == 0 && w == 0 && lane == 0) u[c][0][0] = __byte_perm(t0[c], u[c][0][0], 0x7610);
            }
        }
#pragma unroll
    for (int c = 0; c < NC; c++) fft_stage<NC>(u[c], c, eo, w, lane);
}

template <int NC, bool SHEAR, class Mid>
__device__ __forceinline__ void fft_forward(const uint4 (&a1)[4], const uint4 (&tw)[4], uint32_t eo, uint32_t s2, uint32_t (&X)[NC][2][8], Mid mid) {
    uint32_t dr[8 * NC], di[8 * NC];
    const uint64_t de = mkdesc(eo, 4096, 1024, 1), d2 = mkdesc(s2, 16, 1024, 1);
    wg_fence();
    wgmma_s1(dr, a1[0], de, 0);
    wgmma_s1(di, a1[2], de + (NC == 2 ? 256 : 4), 0);
    wgmma_s1(dr, a1[1], de + 128, 1);
    wgmma_s1(di, a1[3], de + (NC == 2 ? 384 : 132), 1);
    wg_commit();
    mid();
    wg_wait<0>();
#pragma unroll
    for (int c = 0; c < NC; c++) {
        uint4 zr[2], zi[2];
#pragma unroll
        for (int p = 0; p < 2; p++)
#pragma unroll
            for (int i = 0; i < 4; i++) {
                const uint32_t r = dr[8 * c + 4 * p + i], m = di[8 * c + 4 * p + i], tr = u4(tw[p], i), ti = u4(tw[2 + p], i);
                if (SHEAR) {
                    const uint32_t r1 = hfma(tr, m, r), m1 = hfma(ti, r1, m);
                    u4r(zr[p], i) = hfma(tr, m1, r1); u4r(zi[p], i) = m1;
                } else {
                    u4r(zr[p], i) = hfms(m, ti, hmul(r, tr));
                    u4r(zi[p], i) = hfma(m, tr, hmul(r, ti));
                }
            }
        wg_fence();
        wgmma_h32_rs<0>(X[c][0], zi[0], d2 + 2, 0);
        wgmma_h32_rs<0>(X[c][1], zi[1], d2 + 6, 0);
        wgmma_h32_rs<0>(X[c][0], zr[0], d2, 1);
        wgmma_h32_rs<0>(X[c][1], zr[1], d2 + 4, 1);
        wg_commit();
    }
}

template <int NC, class Idle, class Ready, class Staged>
__device__ __forceinline__ void conv_wg(int ch0, int layer, uint32_t eo, uint32_t zb, uint32_t s23, uint32_t kexp, uint32_t epoch, uint32_t st, uint32_t sbar,
                                        int warp, int lane, uint4 (&a1)[4], uint4 (&tw)[4], Idle idle, Ready ready, Staged staged TS_ARG) {
    const int wg = warp >> 2, w = warp & 3, t = 32 * w + lane, q = lane & 3, mi = lane >> 3, mj = lane & 7;
    auto F = [](uint32_t x) { return __uint_as_float(x); };
    uint32_t KH[NC][2][8];
    TS(2);
    fft_forward<NC, false>(a1, tw, eo, s23, KH, [] {});
    named_bar(1 + wg, 128);
    uint4 a4[4];
#pragma unroll
    for (int i = 0; i < 4; i++) if (NC == 2) { tw[i] = ldg_tab(4 + i, t); a4[i] = ldg_tab(12 + i, t); }
    wg_wait<0>();
    TS(4);
    idle();
    uint2 x[NC][2][2];
    const uint32_t ra[2] = {4u * t, 4u * (t ^ 252)};
    ready();
    TS(5);
    auto xload = [&](int i) {
        const unsigned long long v = ld_ll((const unsigned long long*)(g_x1T + (uint32_t)ch0 * XP + ra[(i >> 1) & 1] + ((i >> 2) * XP + 1024 * (i & 1))));
        x[i >> 2][(i >> 1) & 1][i & 1] = make_uint2((uint32_t)v, (uint32_t)(v >> 32));
    };
#pragma unroll
    for (int i = 0; i < 4 * NC; i++) xload(i);
    TS(6);
    if (NC == 1) {
        uint4 s[8];
        TS(1);
#pragma unroll
        for (int i = 0; i < 8; i++) s[i] = make_uint4(layer, 0, 0, 0);
        int spin = 0;
        uint32_t bad;
        do {
            bad = 0;
#pragma unroll
            for (int i = 0; i < 8; i++)
                if (((s[i].x ^ layer) & 1u) == 0) s[i] = ld_ll4((const uint4*)(g_fs[0] + ra[i >> 2] + (SEQ * (i & 1) + 1024 * ((i >> 1) & 1))));
#pragma unroll
            for (int i = 0; i < 8; i++) bad |= ~(s[i].x ^ layer);
        } while ((bad & 1u) && ++spin < (1 << 18));
#pragma unroll
        for (int i = 0; i < 8; i++) sts128(st + i * 2048 + t * 16, s[i]);
        __syncwarp();
        if (lane == 0) mbar_arrive(sbar + 8 * w);
        TS(14);
    }
    for (int spin = 0; spin < (1 << 18); spin++) {
        uint32_t bad = 0;
#pragma unroll
        for (int i = 0; i < 4 * NC; i++) bad |= ~(x[i >> 2][(i >> 1) & 1][i & 1].x ^ layer);
        if (!(bad & 1u)) break;
#pragma unroll
        for (int i = 0; i < 4 * NC; i++) if (((x[i >> 2][(i >> 1) & 1][i & 1].x ^ layer) & 1u) == 0) xload(i);
    }
    __syncwarp();
#pragma unroll
    for (int i = 0; i < 4; i++) if (NC == 1) { tw[i] = ldg_tab(4 + i, t); a4[i] = ldg_tab(12 + i, t); }
    TS(26);
    if (NC == 2) mbar_wait(sbar + 8 * w, 0);
    {
        uint4 s[2][2][2];
        uint32_t u[NC][2][4];
#pragma unroll
        for (int h = 0; h < 2; h++) {
            if (NC == 1 || h == 0) {
#pragma unroll
                for (int i = 4 * h; i < (NC == 1 ? 4 * h + 4 : 8); i++) s[i >> 2][(i >> 1) & 1][i & 1] = lds128(st + i * 2048 + t * 16);
            }
            if (h == 0) TS(7);
#pragma unroll
            for (int c = 0; c < NC; c++)
#pragma unroll
                for (int j = 0; j < 4; j++) {
                    const uint4 &a = s[h][j >> 1][0], &b = s[h][j >> 1][1];
                    const uint32_t xv = (j & 1) ? x[c][h][j >> 1].y : x[c][h][j >> 1].x;
                    u[c][h][j] = pack2h(fmaf(bf_lo(xv), F(u4(a, 2 * (j & 1))), F(u4(b, 2 * (j & 1)))), fmaf(bf_hi(xv), F(u4(a, 2 * (j & 1) + 1)), F(u4(b, 2 * (j & 1) + 1))));
                }
        }
#pragma unroll
        for (int c = 0; c < NC; c++) fft_stage<NC>(u[c], c, eo, w, lane);
    }
    TS(8);
    fence_async_smem();
    TS(9);
    named_bar(1 + wg, 128);
    uint32_t X[NC][2][8], Y[NC][2][8];
    uint32_t oscale[NC];
    fft_forward<NC, true>(a1, tw, eo, s23, X, [&] {
#pragma unroll
        for (int c = 0; c < NC; c++) oscale[c] = (lds32(kexp + 4 * c) + 3u) * 0x00800080u;
        if (layer) {
#pragma unroll
            for (int i = 0; i < 4 * NC; i++) asm volatile("mov.b32 %0, 0;\nmov.b32 %1, 0;" : "=r"(x[i >> 2][(i >> 1) & 1][i & 1].x), "=r"(x[i >> 2][(i >> 1) & 1][i & 1].y));
        }
        TS(3); staged(); if (F_STAG >= 2 && NC == 2 && wg == 1) named_bar(10 + w, 64); });
    if (F_STAG == 2 && NC == 2 && wg == 0) asm volatile("bar.arrive %0, 64;" ::"r"(10 + w) : "memory");
    TS(10);
    const uint64_t d3 = mkdesc(s23 + 4096, 16, 1024, 1);
#pragma unroll
    for (int c = 0; c < NC; c++) {
        wg_wait<NC - 1>();
        TS(11 + c);
        uint4 pr[2], pi[2];
#pragma unroll
        for (int i = 0; i < 4; i++) {
            const uint32_t er = X[c][0][i], ei = X[c][0][4 + i], orr = X[c][1][i], oi = X[c][1][4 + i];
            const uint32_t ar = KH[c][0][i], ai = KH[c][0][4 + i], br = KH[c][1][i], bi = KH[c][1][4 + i];
            u4r(pr[0], i) = hfms(bi, oi, hfma(br, orr, hfms(ai, ei, hmul(ar, er))));
            u4r(pi[0], i) = hfma(bi, orr, hfma(br, oi, hfma(ai, er, hmul(ar, ei))));
            u4r(pr[1], i) = hfms(ai, oi, hfma(ar, orr, hfms(bi, ei, hmul(br, er))));
            u4r(pi[1], i) = hfma(ai, orr, hfma(ar, oi, hfma(bi, er, hmul(br, ei))));
        }
        if (F_STAG == 3 + c && NC == 2 && wg == 0) asm volatile("bar.arrive %0, 64;" ::"r"(10 + w), "r"(pr[0].x ^ pr[1].w ^ pi[0].y ^ pi[1].z) : "memory");
        wg_fence();
        wgmma_h32_rs<0>(Y[c][0], pr[0], d3, 0);
        wgmma_h32_rs<0>(Y[c][1], pr[1], d3 + 4, 0);
        wgmma_h32_rs<0>(Y[c][0], pi[0], d3 + 2, 1);
        wgmma_h32_rs<0>(Y[c][1], pi[1], d3 + 6, 1);
        wg_commit();
    }
#pragma unroll
    for (int c = 0; c < NC; c++) {
        if (c + 1 < NC) wg_wait<1>(); else wg_wait<0>();
        TS(13 + c);
        uint32_t zr[2][4], zi[2][4];
#pragma unroll
        for (int p = 0; p < 2; p++)
#pragma unroll
            for (int i = 0; i < 4; i++) {
                const uint32_t r = Y[c][p][i], m = Y[c][p][4 + i], tr = u4(tw[p], i), ti = u4(tw[2 + p], i);
                const uint32_t r1 = hfms(tr, m, r), m1 = hfms(ti, r1, m);
                zr[i & 1][2 * p + (i >> 1)] = hfms(tr, m1, r1);
                zi[i & 1][2 * p + (i >> 1)] = m1;
            }
        const int kr = 4 * (mj >> 1) + (mj & 1) + 2 * (mj >> 2), ki = kr ^ 2;
#pragma unroll
        for (int h = 0; h < 2; h++) {
            const uint32_t a = zb + (2 * w + h) * 2048;
            stsm_x4(a + ki * 128 + (((4 * c + mi) ^ (ki & 7)) << 4), zi[h][0], zi[h][1], zi[h][2], zi[h][3]);
            stsm_x4(a + kr * 128 + (((4 * c + mi) ^ (kr & 7)) << 4), zr[h][0], zr[h][1], zr[h][2], zr[h][3]);
        }
    }
    TS(15);
    fence_async_smem();
    TS(16);
    named_bar(1 + wg, 128);
    TS(17);
    float acc[16 * NC];
    const uint64_t dz = mkdesc(zb, 4096, 1024, 1);
    wg_fence();
#pragma unroll
    for (int ks = 0; ks < 4; ks++) wgmma_s4(acc, a4[ks], dz + ks * 256, 0x44EEEE44u, ks > 0);
    wg_commit();
    const uint32_t fb = ~lds32(epoch);
    uint32_t mk[NC][3];
#pragma unroll
    for (int c = 0; c < NC; c++) {
        const int k = ((ch0 + c) >> 1) & 3;
        mk[c][2] = !layer && k == 2 * q; mk[c][1] = !layer && k == 2 * q + 1; mk[c][0] = mk[c][2] | layer;
    }
    auto mark = [&](uint32_t v, uint32_t m) { return (v & ~m) | (fb & m); };
    const char* dst[2];
    {
        uint32_t l2;
        asm volatile("mov.u32 %0, %%laneid;" : "=r"(l2));
        const char* base = layer ? (const char*)g_of + (uint32_t)(ch0 / 80) * 327680u + (uint32_t)(ch0 % 80) * 256u : (const char*)g_x2T + (uint32_t)ch0 * (XP * 2u);
#pragma unroll
        for (int h = 0; h < 2; h++) {
            const uint32_t v = (32 * w + l2) ^ (h ? 252u : 0u);
            dst[h] = base + (layer ? (v >> 4) * 20480u + (v & 15u) * 16u : v * 8u);
        }
    }
    wg_wait<0>();
    TS(18);
#pragma unroll
    for (int c = 0; c < NC; c++) {
        uint32_t r[2][4];
#pragma unroll
        for (int j = 0; j < 4; j++) {
            const float* d = acc + 4 * (4 * c + j);
            const uint32_t y0 = pack2(d[0] + d[2], d[1] + d[3]), y1 = pack2(d[0] - d[2], d[1] - d[3]);
            asm("fma.rn.bf16x2 %0, %1, %2, %3;" : "=r"(r[0][j]) : "r"(y0), "r"(oscale[c]), "r"((j & 1) ? x[c][0][j >> 1].y : x[c][0][j >> 1].x));
            asm("fma.rn.bf16x2 %0, %1, %2, %3;" : "=r"(r[1][j]) : "r"(y1), "r"(oscale[c]), "r"((j & 1) ? x[c][1][j >> 1].y : x[c][1][j >> 1].x));
        }
#pragma unroll
        for (int h = 0; h < 2; h++)
            asm volatile("{\n.reg .pred p;\n.reg .b128 t;\n.reg .b64 a, b;\nsetp.ne.u32 p, %5, 0;\nmov.b64 a, {%1, %2};\nmov.b64 b, {%3, %4};\nmov.b128 t, {a, b};\n"
                         "@p st.relaxed.gpu.global.b128 [%0], t;\n@!p st.relaxed.gpu.global.b64 [%6], a;\n@!p st.relaxed.gpu.global.b64 [%6 + 2048], b;\n}"
                         ::"l"(dst[h] + c * 256), "r"(mark(r[h][0], mk[c][0])), "r"(mark(r[h][1], mk[c][1])), "r"(mark(r[h][2], mk[c][2])), "r"(mark(r[h][3], mk[c][1])), "r"(layer), "l"(dst[h] + c * XP * 2) : "memory");
    }
    TS(19);
}

#define Q_S0 8
#define A_HPOS 1
#define A_CSPRE 2
#define R_CONS 192
#define K_CSUN 1
constexpr int K_CSU = K_CSUN;
#define G_MAP 1
#define Q_SP 2
#define X_HINT 1
#define S_FIRST 1
#define A_VLO 4
#define O_KPOS 1
constexpr int Q_ST = 4;
constexpr int Q_AB = 16384, Q_BB = 30720, Q_SB = Q_AB + Q_BB;
constexpr int Q_EROW = 336;
constexpr int Q_ESLOT = 8 * Q_EROW;
constexpr int Q_EOFF = Q_ST * Q_SB;
constexpr int Q_KG = 2 * Q_SB;
static_assert(3 * Q_ESLOT <= 8192 && Q_KG + KG_TABLES <= Q_EOFF + 4096, "exchange slots, kernel generation");
constexpr int F_EO = Q_EOFF, F_S23 = F_EO + 2 * 8192 + 4096, Q_KDUMP = F_S23 + 8192;
constexpr int Q_MISC = Q_KDUMP + 6 * KG_RES;
__host__ __device__ constexpr int w_grp(int j) { return j < 7 ? 2 * Q_SB + 4096 + j * 12800 : 0; }
constexpr int W_RES = Q_AB;
__device__ __forceinline__ int o_slot(int wg, int s) { return W_RES + (((2 * s + 2) & 7) + wg) * 10240; }
__device__ __forceinline__ int w_out(int wg) { return W_RES + (2 + 3 * wg) * 10240; }
static_assert(W_RES + 8 * 10240 == w_grp(0) && w_grp(6) + 12800 <= Q_EOFF && w_grp(3) <= 3 * Q_SB, "phase W layout");

constexpr int Q_WOT = Q_EOFF + 4096;

__device__ unsigned g_epoch;
__device__ __align__(1024) unsigned g_bar[4][16][32];
__device__ __align__(1024) uint4 g_wop[8][80][10][8];
__device__ __align__(1024) uint4 g_csp[8][16][96];
__device__ __align__(1024) uint4 g_stp[16][8][64];
__device__ __align__(1024) uint4 g_sp2[16][8][8][8];
__device__ __align__(1024) uint4 g_halo[128][2][5][32];

struct Bars { uint64_t full[Q_ST], empty[Q_ST], wfull[3], ex[7], res, go, qdone, prep, ardy, hdone, fdone, idx, att[2], wfree, soon[2], st[4], kfree, staged, xland[2]; };
constexpr int NBAR = sizeof(Bars) / 8;
struct OBars { uint64_t full[8], ready[8], empty[8]; };
struct Misc { float cs[240], mean[2][64], rstd[2][72]; Bars bar[2]; OBars ob; KgShared kg; uint32_t epoch, pad; };
#define MISC(f) (sb + Q_MISC + (uint32_t)offsetof(Misc, f))
constexpr int Q_SMEM = Q_MISC + sizeof(Misc) + TS_SMEM;
__host__ __device__ constexpr int bar_count(int i) {
#define BAR_IS(f) (i == offsetof(Bars, f) / 8)
    return (i >= 4 && i < 8) ? 16 : (BAR_IS(go) || (i >= offsetof(Bars, att) / 8 && i < offsetof(Bars, st) / 8)) ? 4 : BAR_IS(qdone) ? 8 : BAR_IS(prep) ? 96 :
           BAR_IS(hdone) ? 6 : BAR_IS(fdone) ? 3 : BAR_IS(kfree) ? 24 : BAR_IS(staged) ? 2 : 1;
}
__device__ __forceinline__ void grid_wait(const unsigned* c, int n, unsigned target, int lane) {
    const unsigned* p = c + 32 * min(lane, n - 1);
    unsigned v;
    int spin = 0;
    do { asm volatile("ld.relaxed.gpu.global.u32 %0, [%1];" : "=r"(v) : "l"(p) : "memory"); } while (!__all_sync(~0u, (int)(v - target) >= 0) && ++spin < (1 << 18));
    fence_acquire();
}
__device__ __forceinline__ void grid_arrive(unsigned* c) {
    fence_release();
    asm volatile("red.relaxed.gpu.global.add.u32 [%0], 1;" ::"l"(c) : "memory");
}

#define TMAP(n) ([] { const CUtensorMap* p_; asm volatile("{\n.reg .b64 t;\nmov.b64 t, fused_kernel_param_" #n ";\ncvta.param.u64 %0, t;\n}" : "=l"(p_)); return p_; }())
extern "C" __global__ void __launch_bounds__(384, 1)
fused_kernel(const SsmParams sp, const __grid_constant__ CUtensorMap mX0, const __grid_constant__ CUtensorMap mX1, const __grid_constant__ CUtensorMap mW,
             const __grid_constant__ CUtensorMap mWr,
             const __grid_constant__ CUtensorMap mRes0, const __grid_constant__ CUtensorMap mRes1, const __grid_constant__ CUtensorMap mOut,
             const __grid_constant__ CUtensorMap mWo, const __grid_constant__ CUtensorMap mFin, const __grid_constant__ CUtensorMap mResA) {
    extern __shared__ __align__(1024) char smraw[];
    const uint32_t sb = s2u(smraw);
    int tid, warp, lane, bx, rank, blk, hg, rot, c0;
    int role;
    {
        const int c = blockIdx.x >> 1, d = c - 41, r = d >= 21 ? 3 : d >= 14 ? 2 : d >= 7 ? 1 : 0;
        const int gp = c < 4 ? 0 : c <= 40 ? (c + 7) & 7 : d - 7 * r + 1;
        const int k = c < 4 ? c : c <= 40 ? (c >> 3) + (gp == 0 ? 3 : gp >= 3 && gp < 7 ? 0 : -1) : (gp >= 3 ? 5 : 4) + r;
        role = G_MAP == 1 ? 16 * k + 2 * gp + (blockIdx.x & 1) : G_MAP == 2 ? 16 * gp + 2 * k + (blockIdx.x & 1) : blockIdx.x;
    }
    auto indices = [&] {
        asm volatile("mov.u32 %0, %%tid.x;" : "=r"(tid));
        asm volatile("mov.u32 %0, %1;" : "=r"(bx) : "r"(role));
        warp = __shfl_sync(~0u, tid >> 5, 0); lane = tid & 31;
        rank = bx & 1; blk = bx & 15; hg = bx >> 4;
        const int u = ((blk >> 1) + hg) & 7;
        rot = (5 * u) >> 2; c0 = 16 * (u & 3);
    };
    indices();
    TS_DECL;
    TS_BEGIN;
#define EPOCH lds32(MISC(epoch))
    int layer = 0;
    uint32_t bars = MISC(bar);
#define BAR(f) (bars + (uint32_t)offsetof(Bars, f))
    auto chunk = [&](int it, int s0) {
        const int i = it < s0 ? it : it - 2;
        return (it >> 1) == (s0 >> 1) ? rot + (it & 1) : i < rot ? i : i + 2;
    };
    auto osrc_of = [&](int j) { return j == 0 ? hg : j - 1 < hg ? j - 1 : j; };
    auto issue_w = [&](uint32_t bb, int it, int lay) {
        const int half = rank;
        const int s = it & (Q_ST - 1);
        const uint32_t fb = bb + 8 * s, db = sb + s * Q_SB + Q_AB + half * 15360;
        const int k0 = chunk(it, Q_SP * lay) * 64 + half * 32;
#pragma unroll
        for (int p = 0; p < 3; p++) tma2d_mc(db + p * 4096, TMAP(3), p * DM + hg * 80, k0, fb, 3);
        tma3d_mc(db + 12288, TMAP(4), hg * 80 + 64, k0, 0, fb, 3);
    };
    auto issue_x = [&](int it) {
        const int s = it & (Q_ST - 1), kc = chunk(it, Q_SP * layer);
        mbar_expect(BAR(full) + 8 * s, Q_SB);
        tma3d(sb + s * Q_SB, TMAP(1) + layer, (layer ? blk : kc) * 64, (layer ? kc : blk) * 64, 0, BAR(full) + 8 * s);
    };
    {
        KgParams kp;
        const uint32_t epoch0 = ldg32(sp.epoch);
        kgen_load(kp, bx * 5, warp, lane, sp);
        if (warp < 8) {
            cluster_arrive_relaxed();
        } else {
            if (elect_one()) {
                if (warp < 10) { prefetch_tmap(TMAP(3)); prefetch_tmap(TMAP(4)); } else prefetch_tmap(warp == 10 ? TMAP(1) : TMAP(8));
                const uint32_t b0 = bars + (warp >= 10 ? sizeof(Bars) : 0);
                if (warp & 1) {
#pragma unroll
                    for (int i = 0; i < NBAR / 2; i++) mbar_init(b0 + i * 8, bar_count(i));
                } else {
#pragma unroll
                    for (int i = NBAR / 2; i < NBAR; i++) mbar_init(b0 + i * 8, bar_count(i));
                }
                fence_mbar_init();
            }
            __syncwarp();
            cluster_arrive_relaxed();
            TS(29);
            cluster_wait();
            TS(27);
            if (elect_one()) {
                if (warp < 10) {
                    issue_w(BAR(full), warp - 8, 0);
                } else if (warp == 10) {
                    issue_x(0); issue_x(1);
                    prefetch_l2((const char*)c_fft + bx * (sizeof(c_fft) / 128), sizeof(c_fft) / 128);
                } else {
                    mbar_expect(BAR(idx), 8192 + 6400);
                    asm volatile("cp.async.bulk.tensor.4d.shared::cluster.global.mbarrier::complete_tx::bytes [%0], [%1, {0, 0, %3, %4}], [%2];"
                                 ::"r"(sb + Q_WOT), "l"(TMAP(8)), "r"(BAR(idx)), "r"(10 * hg), "r"(5 * blk) : "memory");
                    bulk_g2s(sb + F_S23, c_fft + 18 * 512, 8192, BAR(idx));
                }
            }
            __syncwarp();
            TS(30);
        }
        indices();
        kgen_tables(kp, sb + Q_KG, sb + Q_KDUMP, MISC(kg), warp, lane, [&] { if (warp < 8) cluster_wait(); } TS_PASS);
        __syncwarp();
        if (lane == 0) { mbar_arrive_cta(BAR(kfree), 0); mbar_arrive_cta(BAR(kfree), 1); }
        if (warp >= 8) {
            const int t2 = tid - 256;
            float csum[10];
            if (warp < 11 && elect_one()) {
#pragma unroll
                for (int i = 0; i < 8; i++) mbar_init(MISC(ob) + (warp - 8) * 64 + i * 8, warp == 10 ? 4 : 1);
                fence_mbar_init();
            }
            __syncwarp();
            if (t2 == 0) sts32(MISC(epoch), epoch0);
            if (t2 < 64) stg128(&g_sp2[blk][hg][0][0] + t2, make_uint4(0, 0, 0, 0));
            if (t2 >= 64 && t2 < 80) stg128(&g_of[hg][blk][640 * ((t2 >> 3) & 1) + 8 * (73 + (t2 & 6)) + 6 + (t2 & 1)], make_uint4(epoch0, epoch0, epoch0, epoch0));
#pragma unroll
            for (int i = 0; i < 2; i++)
                if (t2 + 128 * i < 160)
                    stg128(g_x2T + (size_t)(5 * bx + 4 * i + (t2 >> 5)) * XP + 1024 + 32 * (t2 & 30) + 8 * (t2 & 1), make_uint4(epoch0, epoch0, epoch0, epoch0));
            if (t2 >= 120) stg128((uint4*)g_fs + 8 * bx + t2 - 120, make_uint4(0, 0, 0, 0));
            if (t2 < 64) stg128(g_x1T + (size_t)(5 * bx + 4) * XP + 64 * (t2 >> 1) + 48 + 8 * (t2 & 1), make_uint4(0, 0, 0, 0));
#pragma unroll
            for (int i = 0; i < 3; i++)
                if (t2 + 128 * i < 320) stg128(&g_halo[bx][0][0][0] + t2 + 128 * i, make_uint4(0, 0, 0, 0));
            named_bar(13, 128);
            if (warp > 8) {
                const int hw = warp - 9, mi = lane >> 3, mj = lane & 7;
                mbar_wait(BAR(idx), 0);
                if (hw == 2 && elect_one()) { bulk_s2g(&g_wop[hg][5 * blk], sb + Q_WOT, 6400); bulk_commit(); }
                __syncwarp();
                mbar_wait(BAR(full), 0);
                mbar_wait(BAR(full) + 8, 0);
#pragma unroll
                for (int f = 0; f < 10; f++) csum[f] = 0.f;
#pragma unroll K_CSU
                for (int G = 0; G < 5; G++) {
                    const int row = c0 + 40 * rank + 8 * G + mj;
                    const uint32_t b = sb + (row >> 6) * Q_SB + Q_AB + ((row >> 5) & 1) * 15360;
                    uint32_t r[10];
                    ldsm_x4_t(r[0], r[1], r[2], r[3], b + hw * 4096 + (row & 31) * 128 + ((mi ^ mj) << 4));
                    ldsm_x4_t(r[4], r[5], r[6], r[7], b + hw * 4096 + (row & 31) * 128 + (((4 + mi) ^ mj) << 4));
                    ldsm_x2_t(r[8], r[9], b + 12288 + hw * 1024 + (row & 31) * 32 + (((mi & 1) ^ (mj >> 2)) << 4));
#pragma unroll
                    for (int f = 0; f < 10; f++) csum[f] += bf_lo(r[f]) + bf_hi(r[f]);
                }
                const int q = lane & 3;
                float t[3];
#pragma unroll
                for (int j = 0; j < 3; j++) {
                    float v[4];
#pragma unroll
                    for (int k = 0; k < 4; k++) v[k] = 4 * j + k < 10 ? csum[4 * j + k] : 0.f;
                    const float a0 = ((q & 2) ? v[2] : v[0]) + __shfl_xor_sync(~0u, (q & 2) ? v[0] : v[2], 2);
                    const float a1 = ((q & 2) ? v[3] : v[1]) + __shfl_xor_sync(~0u, (q & 2) ? v[1] : v[3], 2);
                    t[j] = ((q & 1) ? a1 : a0) + __shfl_xor_sync(~0u, (q & 1) ? a0 : a1, 1);
                }
                st_ll4(&g_csp[hg][blk][tid - 288], ~EPOCH & 1u, __float_as_uint(t[0]), __float_as_uint(t[1]), __float_as_uint(t[2]));
            }
        }
        TS(1);
    }

    uint4 fa1[4], ftw[4];
    auto conv_tables = [&] {
#pragma unroll
        for (int i = 0; i < 4; i++) { fa1[i] = ldg_tab(i, tid & 127); ftw[i] = ldg_tab(8 + i, tid & 127); }
    };
    auto conv_done = [&] {
        if (layer == 0) {
            named_bar(1 + (warp >> 2), 128);
            if ((tid & 127) == 96) {
                mbar_arrive(BAR(fdone));
                grid_arrive(g_bar[2][hg]);
            }
            __syncwarp();
        }
        TS(20);
    };
    if (warp >= 8) {
    asm volatile("setmaxnreg.dec.sync.aligned.u32 %0;" ::"n"(504 - 2 * R_CONS));
    uint32_t ophase = 0;
#pragma unroll 1
    for (; layer < 2; layer++, bars += sizeof(Bars)) {
        indices();
        TS_PHASE(2 * layer);
        if (warp == 8) {
            if (layer) {
                mbar_wait(BAR(fdone) - sizeof(Bars), 0);
                grid_wait(g_bar[2][0], 8, 48 * (EPOCH + 1), lane);
                fence_async_global();
                TS(10);
            }
            if (elect_one()) {
#pragma unroll 1
                for (int it = 2; it < 10; it++) {
                    if (it >= Q_ST) mbar_wait(BAR(empty) + 8 * (it & (Q_ST - 1)), ((it >> 2) - 1) & 1);
                    else if (layer == 0) mbar_wait(BAR(kfree), 0);
                    if (it == Q_ST + Q_SP * layer) mbar_wait(BAR(hdone), 0);
                    issue_x(it);
                    if (layer == 0 || it >= Q_ST) issue_w(BAR(full), it, layer);
                }
                { prefetch_tmap(TMAP(5) + layer); prefetch_tmap(TMAP(7)); prefetch_tmap(TMAP(10)); }
                if (layer == 0) { mbar_wait(BAR(prep), 0); fence_async_global(); }
#pragma unroll 1
                for (int j = 0; j < 8; j++) {
                    const int b = (j + 1) >> 2;
                    const uint32_t fb = BAR(wfull) + 8 * b;
                    if (j == 0 || j == 3 || j == 7) {
                        mbar_wait(BAR(empty) + 8 * ((2 + b) & 3), b < 2);
                        TS(11 + b);
                        mbar_expect(fb, (b == 0 ? 3 : b == 1 ? 4 : 1) * 12800);
                    }
                    bulk_g2s_mc(sb + w_grp(j) + rank * 6400, &g_wop[hg][osrc_of(j) * 10 + rank * 5], 6400, fb, 3);
                }
                mbar_expect(BAR(res), 20480);
                if (layer) {
                    tma3d(sb + W_RES, TMAP(6), blk * 64, hg * 80, 0, BAR(res));
                } else {
#pragma unroll 1
                    for (int p = 0; p < 2; p++) {
                        tma3d(sb + W_RES + p * 10240, TMAP(10), hg * 80, blk * 64, p, BAR(res));
                        tma3d(sb + W_RES + p * 10240 + 8192, TMAP(5), hg * 80 + 64, blk * 64, p, BAR(res));
                    }
                }
            }
            __syncwarp();
        } else {
            const int ht = tid - 288, hw = warp - 9, mi = lane >> 3, mj = lane & 7, g = lane >> 2, q = lane & 3;
            auto F = [](uint32_t x) { return __uint_as_float(x); };
            auto U = [](float x) { return __float_as_uint(x); };
            const uint32_t lb = layer ^ 1, eb = ~EPOCH & 1u;
            if (layer && hw < 2) {
                const bf16* pp = g_x2T + (size_t)(chunk(hw, Q_SP) * 64 + lane) * XP + 1024 + 64 * blk + (lane & 6);
                const uint32_t a = sb + hw * Q_SB + g * 128 + (((2 * q) ^ g) << 4) + 2 * (g & 6);
                mbar_wait(BAR(fdone) - sizeof(Bars), 0);
                uint32_t bad;
                int spin = 0;
                do {
                    uint32_t v0, v1;
                    asm volatile("ld.relaxed.gpu.global.u32 %0, [%1];" : "=r"(v0) : "l"(pp) : "memory");
                    asm volatile("ld.relaxed.gpu.global.u32 %0, [%1];" : "=r"(v1) : "l"(pp + 32 * XP) : "memory");
                    bad = (v0 ^ eb) | (v1 ^ eb);
                } while (__any_sync(~0u, bad & 1u) && ++spin < (1 << 18));
                fence_async_global();
                TS(1);
                spin = 0;
                do {
                    if (elect_one()) {
                        mbar_expect(BAR(xland) + 8 * hw, Q_AB);
                        tma3d(sb + hw * Q_SB, TMAP(2), blk * 64, chunk(hw, Q_SP) * 64, 0, BAR(xland) + 8 * hw);
                    }
                    __syncwarp();
                    mbar_wait(BAR(xland) + 8 * hw, spin & 1);
                    bad = 0;
#pragma unroll
                    for (int i = 0; i < 16; i++) bad |= lds32(a + i * 1024) ^ eb;
                } while (__any_sync(~0u, bad & 1u) && ++spin < (1 << 16));
                if (lane == 0) mbar_expect(BAR(full) + 8 * hw, Q_BB);
                TS(9);
            }
            mbar_wait(BAR(full) + 8 * Q_SP * layer, 0);
            mbar_wait(BAR(full) + 8 * Q_SP * layer + 8, 0);
            if (ht == 0) TSX(2, 2);
            uint32_t xf[3][20];
#pragma unroll
            for (int i = 0; i < 3; i++) {
                const int tile = min(hw + 3 * i, 7);
#pragma unroll
                for (int k = 0; k < 5; k++) {
                    const int ch = c0 + 16 * k + 8 * (mi >> 1), tok = 16 * (tile & 3) + 8 * (mi & 1);
                    const uint32_t a = sb + ((ch >> 6) + Q_SP * layer) * Q_SB + (tile >> 2) * 8192;
                    if (layer == 0) ldsm_x4(xf[i][4 * k], xf[i][4 * k + 1], xf[i][4 * k + 2], xf[i][4 * k + 3], a + (tok + mj) * 128 + ((((ch & 63) >> 3) ^ mj) << 4));
                    else ldsm_x4_t(xf[i][4 * k], xf[i][4 * k + 1], xf[i][4 * k + 2], xf[i][4 * k + 3], a + ((ch & 63) + mj) * 128 + (((tok >> 3) ^ mj) << 4));
                }
            }
            fence_async_smem();
            __syncwarp();
            if (lane == 0) { mbar_arrive_cta(BAR(hdone), 0); mbar_arrive_cta(BAR(hdone), 1); }
            if (ht == 0) TSX(2, 3);
            if (layer == 0) {
                if (hw == 2 && elect_one()) { bulk_wait(); fence_async_global(); grid_arrive(g_bar[3][hg]); }
                __syncwarp();
                mbar_wait(BAR(kfree), 0);
            }
            if (ht == 0) TSX(2, 8);
#pragma unroll 1
            for (int tile = hw; tile < 8; tile += 3) {
                float a[4] = {0.f, 0.f, 0.f, 0.f};
#pragma unroll
                for (int j = 0; j < 20; j++) {
                    const float lo = bf_lo(xf[0][j]), hi = bf_hi(xf[0][j]);
                    a[2 * (j & 1)] += lo + hi; a[2 * (j & 1) + 1] = fmaf(lo, lo, fmaf(hi, hi, a[2 * (j & 1) + 1]));
                    xf[0][j] = xf[1][j]; xf[1][j] = xf[2][j];
                }
#pragma unroll
                for (int j = 0; j < 4; j++) { a[j] += __shfl_xor_sync(~0u, a[j], 1); a[j] += __shfl_xor_sync(~0u, a[j], 2); }
                if (q == 0) st_ll4(&g_stp[blk][hg][8 * tile + g], (U(a[0]) & ~1u) | lb, U(a[1]), U(a[2]), U(a[3]));
            }
            if (ht == 0) TSX(2, 4);
            if (layer == 0) {
                float t[4] = {0.f, 0.f, 0.f, 0.f};
                uint4 v[16];
                int spin = 0;
                uint32_t bad;
                do {
                    bad = 0;
#pragma unroll
                    for (int j = 0; j < 16; j++) v[j] = ld_ll4(&g_csp[hg][j][ht]);
#pragma unroll
                    for (int j = 0; j < 16; j++) bad |= v[j].x ^ eb;
                } while ((bad & 1u) && ++spin < (1 << 18));
#pragma unroll
                for (int j = 0; j < 16; j++) { t[0] += F(v[j].y); t[1] += F(v[j].z); t[2] += F(v[j].w); }
#pragma unroll
                for (int j = 0; j < 3; j++) if (q + 4 * j < 10) sts32(MISC(cs) + 4 * (80 * hw + 20 * (g >> 1) + 2 * (q + 4 * j) + (g & 1)), U(t[j]));
                if (hw == 2) grid_wait(g_bar[3][0], 8, 16 * (EPOCH + 1), lane);
            }
            if (ht == 0) TSX(2, 15);
            if (ht < 80) {
                const bool halo = ht >= 64;
                const int p = halo ? (ht >> 3) & 1 : ht >> 5, i = halo ? (ht & 7) - 8 : 8 + 2 * (ht & 24) + (ht & 7);
                const uint4* src = &g_stp[halo && blk ? blk - 1 : blk][0][halo ? 32 * p + 24 + (ht & 7) : ht];
                uint4 v[8];
                int spin = 0;
                uint32_t bad;
                do {
                    bad = 0;
#pragma unroll
                    for (int j = 0; j < 8; j++) v[j] = ld_ll4(src + 64 * j);
#pragma unroll
                    for (int j = 0; j < 8; j++) bad |= v[j].x ^ lb;
                } while ((bad & 1u) && ++spin < (1 << 18));
                float t[4] = {0.f, 0.f, 0.f, 0.f};
#pragma unroll
                for (int j = 0; j < 8; j++) { t[0] += F(v[j].x); t[1] += F(v[j].y); t[2] += F(v[j].z); t[3] += F(v[j].w); }
                const uint32_t s0 = ln_finish_packed(t[0], t[1]), s1 = ln_finish_packed(t[2], t[3]);
                const uint32_t am = MISC(mean) + 4 * (64 * p + i), ar = MISC(rstd) + 4 * (72 * p + i);
                if (!halo) { sts32(am - 32, U(bf_hi(s0))); sts32(am, U(bf_hi(s1))); sts32(ar, U(frcp(bf_lo(s0)))); }
                sts32(ar + 32, U(frcp(bf_lo(s1))));
            }
            fence_acquire();
            mbar_arrive(BAR(prep));
            if (ht == 0) TSX(2, 5);
        }
        __syncwarp();
        indices();
        auto kstage = [&] {
            const uint4 ko[2] = {ldg_tab(16, tid & 127), ldg_tab(17, tid & 127)};
            conv_tables();
            kernel_stage<1>(ko, sb + Q_KDUMP + 4 * KG_RES, MISC(kg), 4, sb + F_EO + 2 * 8192, warp & 3, lane);
            fence_async_smem();
        };
        if (O_KPOS == 0) kstage();
        {
            const int p = warp & 1;
            const uint32_t fb = EPOCH ^ layer ^ 1, ob = MISC(ob) + 32 * p;
            auto fetch = [&](int j) {
                if (elect_one()) {
                    mbar_expect(ob + 8 * ((j - 1) & 3), 10240);
                    bulk_g2s(sb + o_slot(p, (j - 1) & 3), &g_of[osrc_of(j)][blk][640 * p], 10240, ob + 8 * ((j - 1) & 3));
                }
                __syncwarp();
            };
            if (warp < 10) {
                const uint32_t* pp = &g_of[osrc_of(1 + min(lane >> 2, 6))][blk][640 * p + 8 * (73 + 2 * (lane & 3)) + 7].x;
                mbar_wait(BAR(qdone), 0);
                mbar_wait(BAR(att) + 8 * p, 0);
                uint32_t miss = ~0u;
                int spin = 0;
#pragma unroll 1
                for (int j = 1; j < 8; j++) {
                    while (((miss >> (4 * j - 4)) & 15u) && ++spin < (1 << 18)) {
                        uint32_t v;
                        asm volatile("ld.relaxed.gpu.global.u32 %0, [%1];" : "=r"(v) : "l"(pp) : "memory");
                        miss = __ballot_sync(~0u, (v ^ fb) & 1u);
                        fence_async_global();
                    }
                    if (j == 1) TS(16);
                    if (j > 3) mbar_wait(ob + 128 + 8 * ((j - 1) & 3), layer);
                    fetch(j);
                }
                TS(17);
            } else {
#pragma unroll 1
                for (int j = 1, spin = 0; j < 8;) {
                    const int s = (j - 1) & 3;
                    mbar_wait(ob + 8 * s, (ophase >> s) & 1);
                    ophase ^= 1u << s;
                    const uint32_t a = sb + o_slot(p, s) + (lane >> 2) * 132 + (lane & 3) * 32;
                    uint32_t bad = 0;
#pragma unroll
                    for (int i = 0; i < 10; i++) bad |= lds32(a + i * 1024) ^ fb;
                    if (__any_sync(~0u, bad & 1u) && ++spin < (1 << 16)) { fetch(j); continue; }
                    if (lane == 0) mbar_arrive(ob + 64 + 8 * s);
                    j++;
                }
            }
        }
        TS_PHASE(2 * layer + 1);
        TS(0);
        indices();
        if (O_KPOS == 1) kstage();
        named_bar(3, 128);
        conv_wg<1>(5 * bx + 4, layer, sb + F_EO + 2 * 8192, sb + 2 * Q_SB, sb + F_S23, MISC(kg.kexp) + 16, MISC(epoch), sb + 3 * Q_SB, BAR(st), warp, lane, fa1, ftw,
        [&] {
            if (warp == 9) {
                auto F = [](uint32_t x) { return __uint_as_float(x); };
                mbar_wait(BAR(soon) + 8 * (hg >> 2), 0);
                TS(23);
                const uint4* src = &g_sp2[blk][hg][0][0] + lane;
                uint4* dst = (uint4*)(g_fs[(lane >> 2) & 1] + 1024 * (hg >> 2) + 64 * blk + 16 * (hg & 3)) + (lane & 3);
                const bool up = lane & 8;
#pragma unroll 1
                for (int spin = 0; spin < (1 << 18); spin++) {
                    const uint4 a = ld_ll4(src), b = ld_ll4(src + 32);
                    const bool ok = !__any_sync(~0u, ~((a.x ^ layer) & (b.x ^ layer)) & 1u);
                    const float s0 = F(a.x) + F(b.x), q0 = F(a.y) + F(b.y), s1 = F(a.z) + F(b.z), q1 = F(a.w) + F(b.w);
                    float sm = (up ? s1 : s0) + __shfl_xor_sync(~0u, up ? s0 : s1, 8), sq = (up ? q1 : q0) + __shfl_xor_sync(~0u, up ? q0 : q1, 8);
                    sm += __shfl_xor_sync(~0u, sm, 16); sq += __shfl_xor_sync(~0u, sq, 16);
                    const float m = sm * (1.0f / DM), r = frsq(fmaxf(fmaf(sq, 1.0f / DM, fmaf(-m, m, 1e-5f)), 1e-5f));
                    const uint32_t v = __float_as_uint(lane & 16 ? -m * r : r);
                    const uint32_t v0 = __shfl_sync(~0u, v, 4 * lane), v1 = __shfl_sync(~0u, v, 4 * lane + 1), v2 = __shfl_sync(~0u, v, 4 * lane + 2), v3 = __shfl_sync(~0u, v, 4 * lane + 3);
                    if (ok && lane < 8) st_ll4(dst, (v0 & ~1u) | (layer ^ 1), v1, v2, v3);
                    if (ok) break;
                }
            }
            TS(25);
            mbar_wait(BAR(staged), 0);
        }, [&] { mbar_wait(BAR(ardy), 0); }, [&] {
            if (tid == 352) prefetch_tmap(layer ? TMAP(9) : TMAP(2));
        } TS_PASS);
        conv_done();
    }
    } else {
#pragma unroll 1
    for (; layer < 2; layer++, bars += sizeof(Bars)) {
    indices();
    TS_PHASE(2 * layer);
    const int wg = warp >> 2, w = warp & 3;
    const int mi = lane >> 3, mj = lane & 7, g = lane >> 2, q = lane & 3;
    TS(2);
    float acc[120];
#pragma unroll
    for (int i = 0; i < 120; i++) acc[i] = 0.f;
    auto release = [&](int it) {
        if (lane == 0) { mbar_arrive_cta(BAR(empty) + 8 * (it & (Q_ST - 1)), 0); mbar_arrive_cta(BAR(empty) + 8 * (it & (Q_ST - 1)), 1); }
    };
#pragma unroll 1
    for (int it = 0; it < 10; it++) {
        const int s = it & (Q_ST - 1);
        const uint32_t st = sb + s * Q_SB;
        const bool hold = wg == 1 && it == Q_S0;
        if (hold) {
            wg_wait<0>();
            release(it - 1);
            mbar_wait(BAR(go), 0);
        }
        mbar_wait(BAR(full) + 8 * (s), (it >> 2) & 1);
        if (it < 2) TS(3 + it);
        if (it == 6) TS(5);
        if (it == 9) TS(6);
        const uint64_t da = mkdesc(st + wg * 8192, 16, 1024, 1);
        const uint64_t db = mkdesc(st + Q_AB, 4096, 1024, 1);
        const uint64_t dr = mkdesc(st + Q_AB + 12288, 1024, 256, 3);
        if (layer == 0) {
            wg_fence();
#pragma unroll
            for (int ks = 0; ks < 4; ks++) {
                const int sc = 1;
                wgmma_n192<0, 1>(*(float(*)[96]) & acc[0], da + ks * 2, db + (ks >> 1) * 960 + (ks & 1) * 128, sc);
                wgmma_n48<0, 1>(*(float(*)[24]) & acc[96], da + ks * 2, dr + (ks >> 1) * 960 + (ks & 1) * 32, sc);
            }
            wg_commit();
        } else {
            wg_fence();
#pragma unroll
            for (int ks = 0; ks < 4; ks++) {
                const int sc = 1;
                wgmma_n192<1, 1>(*(float(*)[96]) & acc[0], da + ks * 128, db + (ks >> 1) * 960 + (ks & 1) * 128, sc);
                wgmma_n48<1, 1>(*(float(*)[24]) & acc[96], da + ks * 128, dr + (ks >> 1) * 960 + (ks & 1) * 32, sc);
            }
            wg_commit();
        }
        wg_wait<1>();
        if (it > 0 && !hold) release(it - 1);
    }
    if (wg == 0 && lane == 0) mbar_arrive(BAR(go));
    asm volatile("setmaxnreg.inc.sync.aligned.u32 %0;" ::"n"(R_CONS));
    mbar_wait(BAR(prep), 0);
    const uint32_t ob = layer ^ 1;
    const bool first = (blk == 0 && w == 0);
    const bool sel0 = (2 * q > g), sel1 = (2 * q + 1 > g);
    constexpr float SC = 0.22360679774997896f * 1.4426950408889634f;
    const float m0 = __uint_as_float(lds32(MISC(mean) + 4 * (16 * warp + g))), m1 = __uint_as_float(lds32(MISC(mean) + 4 * (16 * warp + g + 8)));
    uint4 cs[3][5];
    auto cs_load = [&](int p) {
#pragma unroll
        for (int i = 0; i < 5; i++) cs[p][i] = lds128(MISC(cs) + 4 * (80 * p + 20 * q + 4 * i));
    };
    if (A_CSPRE >= 1) cs_load(1);
    if (A_CSPRE >= 2) cs_load(2);
    wg_wait<0>();
    if (A_CSPRE < 1) cs_load(1);
    if (A_CSPRE < 2) cs_load(2);
    TS(7);
    if (lane == 0) mbar_arrive(BAR(qdone));
    uint32_t ql[10], qh[10], kl[10], kh[10], vl[10], vh[10];
    auto fold = [&](int p, int f, int h) {
        const int j = (f < 8) ? 8 * p + f : 24 + 2 * p + (f - 8);
        const float c0 = __uint_as_float(u4(cs[p][f >> 1], 2 * (f & 1))), c1 = __uint_as_float(u4(cs[p][f >> 1], 2 * (f & 1) + 1));
        const float m = h ? m1 : m0;
        return pack2(fmaf(-m, c0, acc[4 * j + 2 * h]), fmaf(-m, c1, acc[4 * j + 2 * h + 1]));
    };
#pragma unroll
    for (int f = 0; f < 10; f++) { vh[f] = fold(2, f, 1); if (f < A_VLO) vl[f] = fold(2, f, 0); }
#pragma unroll
    for (int f = 0; f < 10; f++) kh[f] = fold(1, f, 1);
#pragma unroll
    for (int f = 0; f < A_VLO; f++) asm volatile("" : "+r"(vl[f]));
    {
        const uint32_t mk = w == 3 ? 1u : 0u;
        auto mark = [&](uint32_t& v) { v = (v & ~mk) | (ob & mk); };
        mark(kh[0]); mark(kh[5]); mark(vh[0]); mark(vh[4]); mark(vh[8]);
    }
    if (w == 3) {
        uint4* hp = &g_halo[bx][wg][0][lane];
        st_ll4(hp, kh[0], kh[1], kh[3], kh[4]); st_ll4(hp + 32, kh[5], kh[6], kh[8], kh[9]);
        st_ll4(hp + 64, vh[0], vh[1], vh[2], vh[3]); st_ll4(hp + 96, vh[4], vh[5], vh[6], vh[7]);
        st_ll4(hp + 128, vh[8], vh[9], kh[2], kh[7]);
    } else {
        const uint32_t a = sb + Q_EOFF + wg * 8192 + w * Q_ESLOT + mj * Q_EROW + mi * 16;
        stsm_x4(a, kh[0], kh[1], kh[3], kh[4]);
        stsm_x4(a + 64, kh[5], kh[6], kh[8], kh[9]);
        stsm_x4(a + 128, vh[0], vh[1], vh[2], vh[3]);
        stsm_x4(a + 192, vh[4], vh[5], vh[6], vh[7]);
        stsm_x4(a + 256, vh[8], vh[9], kh[2], kh[7]);
        __syncwarp();
        if (lane == 0) mbar_arrive(BAR(ex) + 8 * warp);
    }
    TS(9);
    cs_load(0);
#pragma unroll
    for (int f = 0; f < 10; f++) { kl[f] = fold(1, f, 0); if (f >= A_VLO) vl[f] = fold(2, f, 0); }
#pragma unroll
    for (int f = 0; f < 10; f++) { ql[f] = fold(0, f, 0); qh[f] = fold(0, f, 1); }
    auto rs = [&](int i) { return __uint_as_float(lds32(MISC(rstd) + 4 * (72 * wg + 16 * w + i))); };
    const float kx0 = rs(2 * q + (sel0 ? 0 : 8)), kx1 = rs(2 * q + (sel1 ? 1 : 9)), ky0 = rs(2 * q + (sel0 ? 8 : 16)), ky1 = rs(2 * q + (sel1 ? 9 : 17));
    const float rx = SC * rs(8 + g), ry = SC * rs(16 + g), cx0 = rx * kx0, cx1 = rx * kx1, cy0 = ry * ky0, cy1 = ry * ky1;
    uint4 hv[5];
    const uint4* hp = &g_halo[bx - 1][wg][0][lane];
    auto prev = [&] {
        if (w > 0) {
            const uint32_t a = sb + Q_EOFF + wg * 8192 + (w - 1) * Q_ESLOT + mj * Q_EROW + mi * 16;
            mbar_wait(BAR(ex) + 8 * (warp - 1), 0);
            ldsm_x4(hv[0].x, hv[0].y, hv[0].z, hv[0].w, a);
            ldsm_x4(hv[1].x, hv[1].y, hv[1].z, hv[1].w, a + 64);
            ldsm_x4_t(hv[2].x, hv[2].y, hv[2].z, hv[2].w, a + 128);
            ldsm_x4_t(hv[3].x, hv[3].y, hv[3].z, hv[3].w, a + 192);
            ldsm_x2_t(hv[4].x, hv[4].y, a + 256);
            ldsm_x2(hv[4].z, hv[4].w, a + 288 - (lane >> 4) * 32);
        } else if (blk > 0) {
#pragma unroll
            for (int f = 0; f < 5; f++) hv[f] = ld_ll4(hp + 32 * f);
        } else {
#pragma unroll
            for (int f = 0; f < 5; f++) hv[f] = make_uint4(0, 0, 0, 0);
        }
    };
    if (A_HPOS == 0) prev();
    uint32_t vt[10][2];
#pragma unroll
    for (int f = 0; f < 10; f++) { vt[f][0] = movm_t(vl[f]); vt[f][1] = movm_t(vh[f]); }
    if (A_HPOS == 1) prev();
    TS(10);
    auto FA = [](int h) { return h == 0 ? 0 : h == 1 ? 3 : h == 2 ? 5 : 8; };
    auto FH = [](int h) { return h < 2 ? 2 : 7; };
    const uint32_t pm = (sel0 ? 0xFFFFu : 0u) | (sel1 ? 0xFFFF0000u : 0u);
    auto softmax = [&](float x0, float x1, float k0, float k1) {
        float mx = fmaxf(x0, x1);
        mx = fmaxf(mx, __shfl_xor_sync(~0u, mx, 1));
        mx = fmaxf(mx, __shfl_xor_sync(~0u, mx, 2));
        x0 = ex2(x0 - mx); x1 = ex2(x1 - mx);
        float sx = x0 + x1;
        sx += __shfl_xor_sync(~0u, sx, 1);
        sx += __shfl_xor_sync(~0u, sx, 2);
        const float ix = frcp(sx);
        return pack2(x0 * k0 * ix, x1 * k1 * ix);
    };
    uint32_t qm[4][2], py[4];
    float sl[4][2];
#pragma unroll
    for (int h = 0; h < 4; h++) {
        const int fa = FA(h), fb = fa + 1, fh = FH(h);
        const bool mine = (h & 1) ? (q >= 2) : (q < 2);
        qm[h][0] = mine ? ql[fh] : 0u; qm[h][1] = mine ? qh[fh] : 0u;
        float S1[4] = {0.f, 0.f, 0.f, 0.f}, S2[4] = {0.f, 0.f, 0.f, 0.f};
        mma16816(S1, ql[fa], qh[fa], ql[fb], qh[fb], kl[fa], kl[fb]); mma1688(S1, qm[h][0], qm[h][1], kl[fh]);
        mma16816(S2, ql[fa], qh[fa], ql[fb], qh[fb], kh[fa], kh[fb]); mma1688(S2, qm[h][0], qm[h][1], kh[fh]);
        sl[h][0] = S1[0]; sl[h][1] = S1[1];
        py[h] = softmax((sel0 ? S1[2] : S2[2]) * cy0, (sel1 ? S1[3] : S2[3]) * cy1, ky0, ky1);
    }
    TS(11);
    if (w == 0 && blk > 0) {
        ll_check5(hv, hp, ob);
#pragma unroll
        for (int f = 2; f < 4; f++) hv[f] = make_uint4(movm_t(hv[f].x), movm_t(hv[f].y), movm_t(hv[f].z), movm_t(hv[f].w));
        hv[4].x = movm_t(hv[4].x); hv[4].y = movm_t(hv[4].y);
    }
    const uint32_t kp[10] = {hv[0].x, hv[0].y, hv[4].z, hv[0].z, hv[0].w, hv[1].x, hv[1].y, hv[4].w, hv[1].z, hv[1].w};
    const uint32_t vp[10] = {hv[2].x, hv[2].y, hv[2].z, hv[2].w, hv[3].x, hv[3].y, hv[3].z, hv[3].w, hv[4].x, hv[4].y};
    TS(12);
    const uint4 ko[2] = {ldg_tab(16, tid & 127), ldg_tab(17, tid & 127)};
    const float bx0 = first && sel0 ? -INFINITY : 0.f, bx1 = first && sel1 ? -INFINITY : 0.f;
    float oacc[10][4];
#pragma unroll
    for (int h = 0; h < 4; h++) {
        const int fa = FA(h), fb = fa + 1, fh = FH(h);
        const bool mine = (h & 1) ? (q >= 2) : (q < 2);
        float S0[4] = {0.f, 0.f, 0.f, 0.f};
        mma16816(S0, ql[fa], qh[fa], ql[fb], qh[fb], kp[fa], kp[fb]); mma1688(S0, qm[h][0], qm[h][1], kp[fh]);
        const uint32_t px = softmax(fmaf(sel0 ? S0[0] : sl[h][0], cx0, bx0), fmaf(sel1 ? S0[1] : sl[h][1], cx1, bx1), kx0, kx1);
#pragma unroll
        for (int i = 0; i < 3; i++) {
            const int f = (i == 0) ? fa : (i == 1) ? fb : fh;
            float O[4] = {0.f, 0.f, 0.f, 0.f};
            mma16816(O, px & ~pm, py[h] & pm, 0u, py[h] & ~pm, vt[f][0], vt[f][1]);
            mma1688(O, px & pm, 0u, vp[f]);
            if (i < 2 || !(h & 1) || mine) { oacc[f][0] = O[0]; oacc[f][1] = O[1]; oacc[f][2] = O[2]; oacc[f][3] = O[3]; }
        }
    }
    TS(13);
    float aw[40];
    {
        const uint32_t fb = EPOCH ^ ob, mk[2] = {q == 0 || mj == 2 * w, q == 0 || mj == 2 * w + 1};
        uint32_t* dst = &g_of[hg][blk][640 * wg + 16 * w].x + lane;
        uint4 of[5];
#pragma unroll
        for (int i = 0; i < 20; i++) {
            const uint32_t v = (pack2(oacc[i >> 1][2 * (i & 1)], oacc[i >> 1][2 * (i & 1) + 1]) & ~mk[i & 1]) | (fb & mk[i & 1]);
            u4r(of[i >> 2], i & 3) = v;
            asm volatile("st.relaxed.gpu.global.u32 [%0], %1;" ::"l"(dst + 256 * (i >> 1) + 32 * (i & 1)), "r"(v) : "memory");
        }
        if (lane == 0) mbar_arrive(BAR(att) + 8 * wg);
        TS(14);
        mbar_wait(BAR(wfull), 0);
        const uint64_t dm = mkdesc(sb + w_grp(0), 1280, 128, 0);
        wg_fence();
#pragma unroll
        for (int k = 0; k < 5; k++) wgmma_rs80(aw, of[k], dm + k * 160, k > 0);
        wg_commit();
    }
    const uint32_t obar = MISC(ob) + 32 * wg;
    named_bar(1 + wg, 128);
    kernel_stage<2>(ko, sb + Q_KDUMP + 2 * wg * KG_RES, MISC(kg), 2 * wg, sb + F_EO + wg * 8192, w, lane);
    TS(15);
    uint32_t res[20];
    mbar_wait(BAR(res), 0);
    const uint32_t ta = (8 * (mi >> 1) + mj) * 128 + (((2 * w + (mi & 1)) ^ mj) << 4);
    if (layer == 0) {
        const int tok = 16 * w + 8 * (mi & 1) + mj;
#pragma unroll
        for (int k = 0; k < 4; k++)
            ldsm_x4(res[4 * k], res[4 * k + 1], res[4 * k + 2], res[4 * k + 3], sb + W_RES + wg * 10240 + tok * 128 + (((2 * k + (mi >> 1)) ^ mj) << 4));
        ldsm_x4(res[16], res[17], res[18], res[19], sb + W_RES + wg * 10240 + 8192 + tok * 32 + (((mi >> 1) ^ (mj >> 2)) << 4));
    } else {
#pragma unroll
        for (int k = 0; k < 5; k++) ldsm_x4_t(res[4 * k], res[4 * k + 1], res[4 * k + 2], res[4 * k + 3], sb + W_RES + wg * 10240 + k * 2048 + ta);
    }
    fence_async_smem();
    __syncwarp();
    if (lane == 0) mbar_arrive(obar + 128 + 24);
    conv_tables();
    wg_wait<0>();
    TS(8);
#pragma unroll 1
    for (int j = 1; j < 8; j++) {
        const int s = (j - 1) & 3;
        const uint64_t da = mkdesc(sb + o_slot(wg, s), 1024, 128, 0), dm = mkdesc(sb + w_grp(j), 1280, 128, 0);
        if (s == 2) mbar_wait(BAR(wfull) + 2 * (j + 1), 0);
        mbar_wait(obar + 64 + 8 * s, s == 3 ? layer : j > 4);
        if (j == 1) TS(17);
        if (j == 5) TS(18);
        wg_fence();
#pragma unroll
        for (int k = 0; k < 5; k++) wgmma_ss80(aw, da + k * 128, dm + k * 160);
        wg_commit();
        wg_wait<1>();
        if (j > 1 && j < 5 && lane == 0) mbar_arrive(obar + 128 + 8 * (j - 2));
    }
    if (lane == 0) mbar_arrive(BAR(soon) + 8 * wg);
    named_bar(1 + wg, 128);
    wg_wait<0>();
    TS(19);
#pragma unroll
    for (int i = 0; i < 20; i++) {
        const uint32_t y = pack2(aw[2 * i], aw[2 * i + 1]);
        asm("add.rn.bf16x2 %0, %0, %1;" : "+r"(res[i]) : "r"(y));
    }
    auto stage_out = [&] {
        const uint32_t mk = (g & 3) ? 0u : 0x00010001u;
#pragma unroll
        for (int k = 0; k < 5; k++) {
            uint32_t m[4];
#pragma unroll
            for (int i = 0; i < 4; i++) m[i] = (res[4 * k + i] & ~mk) | (mk & (0u - ob));
            stsm_x4_t(sb + w_out(wg) + k * 2048 + ta, m[0], m[1], m[2], m[3]);
        }
        fence_async_smem();
        named_bar(1 + wg, 128);
        if (w == 0 && elect_one()) {
            asm volatile("cp.async.bulk.tensor.2d.global.shared::cta.bulk_group [%0, {%2, %3}], [%1];"
                         ::"l"(TMAP(7)), "r"(sb + w_out(wg)), "r"(1024 * wg + 64 * blk), "r"(hg * 80) : "memory");
            bulk_commit();
            mbar_arrive(BAR(staged));
        }
        __syncwarp();
        TS(20);
    };
    if (!S_FIRST) stage_out();
    {
        float sm[4] = {0.f, 0.f, 0.f, 0.f}, d0[4] = {0.f, 0.f, 0.f, 0.f}, d1[4] = {0.f, 0.f, 0.f, 0.f};
#pragma unroll
        for (int k = 0; k < 5; k++) {
            mma16816(sm, res[4 * k], res[4 * k + 1], res[4 * k + 2], res[4 * k + 3], 0x3F803F80u, 0x3F803F80u);
            mma16816(d0, res[4 * k], res[4 * k + 1], res[4 * k + 2], res[4 * k + 3], res[4 * k], res[4 * k + 2]);
            mma16816(d1, res[4 * k], res[4 * k + 1], res[4 * k + 2], res[4 * k + 3], res[4 * k + 1], res[4 * k + 3]);
        }
        if (q == (g >> 1))
            st_ll4(&g_sp2[blk][warp][hg][g], (__float_as_uint(sm[0]) & ~1u) | ob, __float_as_uint((g & 1) ? d0[1] : d0[0]), __float_as_uint(sm[2]),
                   __float_as_uint((g & 1) ? d1[3] : d1[2]));
    }
    TS(23);
    if (S_FIRST) stage_out();
    if (layer) {
#pragma unroll
        for (int k = 0; k < 5; k++) stsm_x4_t(sb + W_RES + wg * 10240 + k * 2048 + ta, res[4 * k], res[4 * k + 1], res[4 * k + 2], res[4 * k + 3]);
    }
    TS(22);
    TS_PHASE(2 * layer + 1);
    TS(0);
    indices();
    conv_wg<2>(5 * bx + 2 * (warp >> 2), layer, sb + F_EO + (warp >> 2) * 8192, sb + (warp >> 2) * Q_SB, sb + F_S23, MISC(kg.kexp) + 8 * (warp >> 2),
               MISC(epoch), sb + 3 * Q_SB, BAR(st), warp, lane, fa1, ftw, [&] {
        if ((warp & 3) == 0 && elect_one()) {
            asm volatile("cp.async.bulk.wait_group.read 0;" ::: "memory");
            if (layer == 0) { mbar_arrive_cta(BAR(wfree), 0); mbar_arrive_cta(BAR(wfree), 1); }
        }
        __syncwarp();
    }, [&] {
        if (warp == 0) {
            const bf16* pp = g_x1T + (size_t)(5 * bx + 4) * XP + 64 * lane + 60;
            mbar_wait(BAR(staged), 0);
            uint32_t v;
            int spin = 0;
            if (X_HINT) do { asm volatile("ld.relaxed.gpu.global.u32 %0, [%1];" : "=r"(v) : "l"(pp) : "memory"); } while (__any_sync(~0u, ~(v ^ layer) & 1u) && ++spin < (1 << 18));
            if (lane == 0) mbar_arrive(BAR(ardy));
        } else {
            mbar_wait(BAR(ardy), 0);
        }
    }, [&] {
        if (layer == 0 && warp >= 4 && elect_one()) { mbar_wait(BAR(wfree), 0); issue_w(BAR(full) + sizeof(Bars), warp - 4, 1); }
        __syncwarp();
    } TS_PASS);
    conv_done();
    asm volatile("setmaxnreg.dec.sync.aligned.u32 168;");
    }
    named_bar(1 + (warp >> 2), 128);
    asm volatile("setmaxnreg.dec.sync.aligned.u32 %0;" ::"n"(504 - 2 * R_CONS));
    }
    indices();
    const int cq = 4 * (warp >> 1) + (lane & 3), tg = 8 * (warp & 1) + (lane >> 2);
    const uint32_t fb = ~EPOCH & 1u;
    uint2 xr[4][2];
    __syncthreads();
    if (tid < 320) {
#pragma unroll
        for (int i = 0; i < 8; i++) {
            const int ch = 4 * cq + (i >> 1);
            asm volatile("ld.shared.v2.u32 {%0, %1}, [%2];" : "=r"(xr[i >> 1][i & 1].x), "=r"(xr[i >> 1][i & 1].y)
                         : "r"(sb + W_RES + (i & 1) * 10240 + ch * 128 + (((tg >> 1) ^ (ch & 7)) << 4) + (tg & 1) * 8) : "memory");
        }
    }
    if (tid < 320) {
        const uint4* src = &g_of[hg][blk][64 * cq + tg];
        uint4 v[4];
#pragma unroll
        for (int i = 0; i < 4; i++) v[i] = make_uint4(~fb, 0, 0, 0);
        int spin = 0;
        while (true) {
#pragma unroll
            for (int i = 0; i < 4; i++) if ((v[i].x ^ fb) & 1u) v[i] = ld_ll4(src + 16 * i);
            if (!(((v[0].x ^ fb) | (v[1].x ^ fb) | (v[2].x ^ fb) | (v[3].x ^ fb)) & 1u) || ++spin >= (1 << 18)) break;
        }
        TS(21);
#pragma unroll
        for (int i = 0; i < 16; i++) asm("add.rn.bf16x2 %0, %0, %1;" : "+r"(u4r(v[i >> 2], i & 3)) : "r"((i & 1) ? xr[i >> 2][(i >> 1) & 1].y : xr[i >> 2][(i >> 1) & 1].x));
#pragma unroll
        for (int j = 0; j < 8; j++) {
            const uint32_t sel = (j & 2) ? 0x7632 : 0x5410;
            const int k = 2 * (j & 1) + (j >> 2);
            asm volatile("st.shared.v2.u32 [%0], {%1, %2};" ::"r"(sb + 2 * Q_SB + (16 * j + tg) * 160 + cq * 8),
                         "r"(__byte_perm(u4(v[0], k), u4(v[1], k), sel)), "r"(__byte_perm(u4(v[2], k), u4(v[3], k), sel)) : "memory");
        }
        fence_async_smem();
    }
    __syncthreads();
    if (warp == 0 && elect_one()) {
        asm volatile("cp.async.bulk.tensor.3d.global.shared::cta.bulk_group [%0, {%2, %3, 0}], [%1];" ::"l"(TMAP(9)), "r"(sb + 2 * Q_SB), "r"(80 * hg), "r"(16 * blk) : "memory");
        bulk_commit();
        asm volatile("cp.async.bulk.wait_group.read 0;" ::: "memory");
    }
    if (bx == 0 && tid == 0) g_epoch = (EPOCH + 1) & 0x3FFFFFFFu;
    TS(22);
    TS_END;
}
typedef CUresult (*EncodeTiledFn)(CUtensorMap*, CUtensorMapDataType, cuuint32_t, void*, const cuuint64_t*, const cuuint64_t*, const cuuint32_t*,
                                  const cuuint32_t*, CUtensorMapInterleave, CUtensorMapSwizzle, CUtensorMapL2promotion, CUtensorMapFloatOOBfill);

static void make_map(EncodeTiledFn enc, CUtensorMap* m, const void* base, int rank, const cuuint64_t* dims, const cuuint64_t* strides,
                     const cuuint32_t* box, CUtensorMapSwizzle sw) {
    cuuint32_t es[4] = {1, 1, 1, 1};
    enc(m, CU_TENSOR_MAP_DATA_TYPE_BFLOAT16, rank, (void*)base, dims, strides, box, es, CU_TENSOR_MAP_INTERLEAVE_NONE, sw,
        sw == CU_TENSOR_MAP_SWIZZLE_128B ? CU_TENSOR_MAP_L2_PROMOTION_L2_128B : CU_TENSOR_MAP_L2_PROMOTION_NONE, CU_TENSOR_MAP_FLOAT_OOB_FILL_NONE);
}

template <typename... KArgs, typename... Args>
static void launch(void (*kern)(KArgs...), int grid, int block, int smem, int cluster, bool pdl, Args... args) {
    cudaLaunchConfig_t cfg = {};
    cfg.gridDim = dim3(grid); cfg.blockDim = dim3(block); cfg.dynamicSmemBytes = smem; cfg.stream = cudaStreamPerThread;
    cudaLaunchAttribute at[2];
    int n = 0;
    if (cluster > 1) { at[n].id = cudaLaunchAttributeClusterDimension; at[n].val.clusterDim.x = cluster; at[n].val.clusterDim.y = 1; at[n].val.clusterDim.z = 1; n++; }
    if (pdl) { at[n].id = cudaLaunchAttributeProgrammaticStreamSerialization; at[n].val.programmaticStreamSerializationAllowed = 1; n++; }
    cfg.attrs = at; cfg.numAttrs = n;
    cudaLaunchKernelEx(&cfg, kern, KArgs(args)...);
}

struct HostState {
    bool ready = false;
    const void* key[4] = {nullptr, nullptr, nullptr, nullptr};
    CUtensorMap mX[2], mRes[2], mW, mWr, mWo, mOut, mFin, mResA;
    bf16 *x1T, *x2T;
    unsigned* epoch;
};

extern "C" void kernel_launch(void* const* d_in, const int* in_sizes, int n_in, void* d_out, int out_size) {
    const bf16* x = (const bf16*)d_in[0];
    const bf16* wqkv = (const bf16*)d_in[1];
    const bf16* wo = (const bf16*)d_in[2];
    const bf16* lar = (const bf16*)d_in[4];
    const bf16* aim = (const bf16*)d_in[5];
    const bf16* cre = (const bf16*)d_in[6];
    const bf16* cim = (const bf16*)d_in[7];
    const bf16* logdt = (const bf16*)d_in[8];
    const bf16* dskip = (const bf16*)d_in[9];
    static HostState hs;
    if (!hs.ready || hs.key[0] != wqkv || hs.key[1] != wo || hs.key[2] != x || hs.key[3] != d_out) {
        void* fn = nullptr;
        cudaDriverEntryPointQueryResult qr;
        cudaGetDriverEntryPoint("cuTensorMapEncodeTiled", &fn, cudaEnableDefault, &qr);
        EncodeTiledFn enc = (EncodeTiledFn)fn;
        cudaGetSymbolAddress((void**)&hs.epoch, g_epoch);
        cudaGetSymbolAddress((void**)&hs.x1T, g_x1T);
        cudaGetSymbolAddress((void**)&hs.x2T, g_x2T);
        {
            cuuint64_t d[3] = {DM, SEQ / 2, 2}, s[2] = {DM * 4, DM * 2};
            cuuint32_t b[3] = {64, 64, 2}, ba[3] = {64, 64, 1}, br[3] = {16, 64, 1};
            make_map(enc, &hs.mX[0], x, 3, d, s, b, CU_TENSOR_MAP_SWIZZLE_128B);
            make_map(enc, &hs.mResA, x, 3, d, s, ba, CU_TENSOR_MAP_SWIZZLE_128B);
            make_map(enc, &hs.mRes[0], x, 3, d, s, br, CU_TENSOR_MAP_SWIZZLE_32B);
            cuuint64_t d2[3] = {SEQ / 2, DM, 2}, s2[2] = {XP * 2, SEQ};
            cuuint32_t b2[3] = {64, 80, 2};
            make_map(enc, &hs.mX[1], hs.x2T, 3, d2, s2, b, CU_TENSOR_MAP_SWIZZLE_128B);
            make_map(enc, &hs.mRes[1], hs.x2T, 3, d2, s2, b2, CU_TENSOR_MAP_SWIZZLE_128B);
            cuuint64_t d3[2] = {SEQ, DM};
            make_map(enc, &hs.mOut, hs.x1T, 2, d3, s2, b2, CU_TENSOR_MAP_SWIZZLE_128B);
        }
        { cuuint64_t d[2] = {3 * DM, DM}, s[1] = {3 * DM * 2}; cuuint32_t b[2] = {64, 32};
          make_map(enc, &hs.mW, wqkv, 2, d, s, b, CU_TENSOR_MAP_SWIZZLE_128B); }
        { cuuint64_t d[3] = {DM, DM, 3}, s[2] = {3 * DM * 2, DM * 2}; cuuint32_t b[3] = {16, 32, 3};
          make_map(enc, &hs.mWr, wqkv, 3, d, s, b, CU_TENSOR_MAP_SWIZZLE_32B); }
        { cuuint64_t d[4] = {8, 8, DM / 8, DM / 8}, s[3] = {DM * 2, 16, DM * 16}; cuuint32_t b[4] = {8, 8, 10, 5};
          make_map(enc, &hs.mWo, wo, 4, d, s, b, CU_TENSOR_MAP_SWIZZLE_NONE); }
        { cuuint64_t d[3] = {DM, SEQ / 8, 8}, s[2] = {DM * 16, DM * 2}; cuuint32_t b[3] = {80, 16, 8};
          make_map(enc, &hs.mFin, d_out, 3, d, s, b, CU_TENSOR_MAP_SWIZZLE_NONE); }
        cudaFuncSetAttribute(fused_kernel, cudaFuncAttributeMaxDynamicSharedMemorySize, Q_SMEM);
        hs.key[0] = wqkv; hs.key[1] = wo; hs.key[2] = x; hs.key[3] = d_out;
        hs.ready = true;
    }
    const SsmParams sp = {lar, aim, cre, cim, logdt, dskip, hs.epoch};
    launch(fused_kernel, 128, 384, Q_SMEM, 2, false, sp, hs.mX[0], hs.mX[1], hs.mW, hs.mWr, hs.mRes[0], hs.mRes[1], hs.mOut, hs.mWo, hs.mFin, hs.mResA);
}
```

```cpp
#include <cuda_runtime.h>
#include <cuda.h>
#include <cuda_bf16.h>
#include <cuda_fp16.h>
#include <stdint.h>

typedef __nv_bfloat16 bf16;

constexpr int SEQ = 2048;
constexpr int DM  = 640;
constexpr int XP  = SEQ + 64;
constexpr int NMODE = 192;

__device__ __forceinline__ uint32_t s2u(const void* p) { return (uint32_t)__cvta_generic_to_shared(p); }
__device__ __forceinline__ void mbar_init(uint32_t b, int c) { asm volatile("mbarrier.init.shared::cta.b64 [%0], %1;" ::"r"(b), "r"(c)); }
__device__ __forceinline__ void mbar_expect(uint32_t b, uint32_t bytes) { asm volatile("mbarrier.arrive.expect_tx.shared::cta.b64 _, [%0], %1;" ::"r"(b), "r"(bytes) : "memory"); }
__device__ __forceinline__ void mbar_arrive(uint32_t b) { asm volatile("mbarrier.arrive.shared::cta.b64 _, [%0];" ::"r"(b) : "memory"); }
__device__ __forceinline__ void mbar_arrive_cta(uint32_t b, uint32_t cta) {
    asm volatile("{\n.reg .b32 ra;\nmapa.shared::cluster.u32 ra, %0, %1;\nmbarrier.arrive.shared::cluster.b64 _, [ra];\n}" ::"r"(b), "r"(cta) : "memory");
}
__device__ __forceinline__ void mbar_wait(uint32_t b, uint32_t ph) {
#ifdef M_SAFE
    asm volatile("{\n.reg .pred p;\n.reg .u32 n;\nmbarrier.try_wait.parity.shared::cta.b64 p, [%0], %1;\n@p bra D;\nmov.u32 n, 0;\n"
                 "W: mbarrier.try_wait.parity.shared::cta.b64 p, [%0], %1;\n@p bra D;\nadd.u32 n, n, 1;\nsetp.lt.u32 p, n, 4194304;\n@p bra W;\ntrap;\nD:\n}"
                 ::"r"(b), "r"(ph) : "memory");
#else
    asm volatile("{\n.reg .pred p;\nW: mbarrier.try_wait.parity.shared::cta.b64 p, [%0], %1;\n@!p bra W;\n}" ::"r"(b), "r"(ph) : "memory");
#endif
}
__device__ __forceinline__ void fence_mbar_init() { asm volatile("fence.mbarrier_init.release.cluster;" ::: "memory"); }
__device__ __forceinline__ void cluster_sync() { asm volatile("barrier.cluster.arrive.aligned;\nbarrier.cluster.wait.aligned;" ::: "memory"); }
__device__ __forceinline__ void pdl_wait() { asm volatile("griddepcontrol.wait;" ::: "memory"); }
__device__ __forceinline__ void pdl_launch() { asm volatile("griddepcontrol.launch_dependents;" ::: "memory"); }
__device__ __forceinline__ void named_bar(int id, int n) { asm volatile("bar.sync %0, %1;" ::"r"(id), "r"(n) : "memory"); }
__device__ __forceinline__ void fence_async_smem() { asm volatile("fence.proxy.async.shared::cta;" ::: "memory"); }

__device__ __forceinline__ void tma2d(uint32_t dst, const CUtensorMap* m, int c0, int c1, uint32_t bar) {
    asm volatile("cp.async.bulk.tensor.2d.shared::cluster.global.mbarrier::complete_tx::bytes [%0], [%1, {%3, %4}], [%2];"
                 ::"r"(dst), "l"(m), "r"(bar), "r"(c0), "r"(c1) : "memory");
}
__device__ __forceinline__ void tma2d_mc(uint32_t dst, const CUtensorMap* m, int c0, int c1, uint32_t bar, uint16_t mask) {
    asm volatile("cp.async.bulk.tensor.2d.shared::cluster.global.mbarrier::complete_tx::bytes.multicast::cluster [%0], [%1, {%3, %4}], [%2], %5;"
                 ::"r"(dst), "l"(m), "r"(bar), "r"(c0), "r"(c1), "h"(mask) : "memory");
}
__device__ __forceinline__ void tma3d(uint32_t dst, const CUtensorMap* m, int c0, int c1, int c2, uint32_t bar) {
    asm volatile("cp.async.bulk.tensor.3d.shared::cluster.global.mbarrier::complete_tx::bytes [%0], [%1, {%3, %4, %5}], [%2];"
                 ::"r"(dst), "l"(m), "r"(bar), "r"(c0), "r"(c1), "r"(c2) : "memory");
}
__device__ __forceinline__ void tma3d_mc(uint32_t dst, const CUtensorMap* m, int c0, int c1, int c2, uint32_t bar, uint16_t mask) {
    asm volatile("cp.async.bulk.tensor.3d.shared::cluster.global.mbarrier::complete_tx::bytes.multicast::cluster [%0], [%1, {%3, %4, %5}], [%2], %6;"
                 ::"r"(dst), "l"(m), "r"(bar), "r"(c0), "r"(c1), "r"(c2), "h"(mask) : "memory");
}
__device__ __forceinline__ void bulk_g2s(uint32_t dst, const void* src, uint32_t bytes, uint32_t bar) {
    asm volatile("cp.async.bulk.shared::cluster.global.mbarrier::complete_tx::bytes [%0], [%1], %2, [%3];"
                 ::"r"(dst), "l"(src), "r"(bytes), "r"(bar) : "memory");
}
__device__ __forceinline__ void bulk_g2s_mc(uint32_t dst, const void* src, uint32_t bytes, uint32_t bar, uint16_t mask) {
    asm volatile("cp.async.bulk.shared::cluster.global.mbarrier::complete_tx::bytes.multicast::cluster [%0], [%1], %2, [%3], %4;"
                 ::"r"(dst), "l"(src), "r"(bytes), "r"(bar), "h"(mask) : "memory");
}
__device__ __forceinline__ void prefetch_l2(const void* p, uint32_t bytes) { asm volatile("cp.async.bulk.prefetch.L2.global [%0], %1;" ::"l"(p), "r"(bytes) : "memory"); }
__device__ __forceinline__ void prefetch_tmap(const CUtensorMap* m) { asm volatile("prefetch.tensormap [%0];" ::"l"(m) : "memory"); }

__device__ __forceinline__ void wg_fence() { asm volatile("wgmma.fence.sync.aligned;" ::: "memory"); }
__device__ __forceinline__ void wg_commit() { asm volatile("wgmma.commit_group.sync.aligned;" ::: "memory"); }
template <int N> __device__ __forceinline__ void wg_wait() { asm volatile("wgmma.wait_group.sync.aligned %0;" ::"n"(N) : "memory"); }
__device__ __forceinline__ uint64_t mkdesc(uint32_t addr, uint32_t lbo, uint32_t sbo, uint32_t mode) {
    return (uint64_t)((addr & 0x3FFFF) >> 4) | ((uint64_t)(lbo >> 4) << 16) | ((uint64_t)(sbo >> 4) << 32) | ((uint64_t)mode << 62);
}

__device__ __forceinline__ void mma16816(float (&c)[4], uint32_t a0, uint32_t a1, uint32_t a2, uint32_t a3, uint32_t b0, uint32_t b1) {
    asm("mma.sync.aligned.m16n8k16.row.col.f32.bf16.bf16.f32 {%0,%1,%2,%3},{%4,%5,%6,%7},{%8,%9},{%0,%1,%2,%3};"
                 : "+f"(c[0]), "+f"(c[1]), "+f"(c[2]), "+f"(c[3]) : "r"(a0), "r"(a1), "r"(a2), "r"(a3), "r"(b0), "r"(b1));
}
__device__ __forceinline__ void mma1688(float (&c)[4], uint32_t a0, uint32_t a1, uint32_t b0) {
    asm("mma.sync.aligned.m16n8k8.row.col.f32.bf16.bf16.f32 {%0,%1,%2,%3},{%4,%5},{%6},{%0,%1,%2,%3};"
                 : "+f"(c[0]), "+f"(c[1]), "+f"(c[2]), "+f"(c[3]) : "r"(a0), "r"(a1), "r"(b0));
}
__device__ __forceinline__ void ldsm_x4(uint32_t& r0, uint32_t& r1, uint32_t& r2, uint32_t& r3, uint32_t a) {
    asm volatile("ldmatrix.sync.aligned.m8n8.x4.shared.b16 {%0,%1,%2,%3}, [%4];" : "=r"(r0), "=r"(r1), "=r"(r2), "=r"(r3) : "r"(a) : "memory");
}
__device__ __forceinline__ void ldsm_x4_t(uint32_t& r0, uint32_t& r1, uint32_t& r2, uint32_t& r3, uint32_t a) {
    asm volatile("ldmatrix.sync.aligned.m8n8.x4.trans.shared.b16 {%0,%1,%2,%3}, [%4];" : "=r"(r0), "=r"(r1), "=r"(r2), "=r"(r3) : "r"(a) : "memory");
}
__device__ __forceinline__ void ldsm_x2(uint32_t& r0, uint32_t& r1, uint32_t a) {
    asm volatile("ldmatrix.sync.aligned.m8n8.x2.shared.b16 {%0,%1}, [%2];" : "=r"(r0), "=r"(r1) : "r"(a) : "memory");
}
__device__ __forceinline__ void ldsm_x2_t(uint32_t& r0, uint32_t& r1, uint32_t a) {
    asm volatile("ldmatrix.sync.aligned.m8n8.x2.trans.shared.b16 {%0,%1}, [%2];" : "=r"(r0), "=r"(r1) : "r"(a) : "memory");
}
__device__ __forceinline__ void stsm_x4(uint32_t a, uint32_t r0, uint32_t r1, uint32_t r2, uint32_t r3) {
    asm volatile("stmatrix.sync.aligned.m8n8.x4.shared.b16 [%0], {%1,%2,%3,%4};" ::"r"(a), "r"(r0), "r"(r1), "r"(r2), "r"(r3) : "memory");
}
__device__ __forceinline__ void stsm_x4_t(uint32_t a, uint32_t r0, uint32_t r1, uint32_t r2, uint32_t r3) {
    asm volatile("stmatrix.sync.aligned.m8n8.x4.trans.shared.b16 [%0], {%1,%2,%3,%4};" ::"r"(a), "r"(r0), "r"(r1), "r"(r2), "r"(r3) : "memory");
}
__device__ __forceinline__ void stsm_x2(uint32_t a, uint32_t r0, uint32_t r1) {
    asm volatile("stmatrix.sync.aligned.m8n8.x2.shared.b16 [%0], {%1,%2};" ::"r"(a), "r"(r0), "r"(r1) : "memory");
}
__device__ __forceinline__ uint32_t movm_t(uint32_t a) {
    uint32_t d;
    asm volatile("movmatrix.sync.aligned.m8n8.trans.b16 %0, %1;" : "=r"(d) : "r"(a));
    return d;
}
__device__ __forceinline__ uint32_t lds32(uint32_t a) { uint32_t v; asm volatile("ld.shared.u32 %0, [%1];" : "=r"(v) : "r"(a) : "memory"); return v; }
__device__ __forceinline__ uint32_t ldsv32(uint32_t a) { uint32_t v; asm volatile("ld.volatile.shared.u32 %0, [%1];" : "=r"(v) : "r"(a) : "memory"); return v; }
__device__ __forceinline__ void sts32(uint32_t a, uint32_t v) { asm volatile("st.shared.u32 [%0], %1;" ::"r"(a), "r"(v) : "memory"); }
__device__ __forceinline__ uint4 lds128(uint32_t a) { uint4 v; asm volatile("ld.shared.v4.u32 {%0,%1,%2,%3}, [%4];" : "=r"(v.x), "=r"(v.y), "=r"(v.z), "=r"(v.w) : "r"(a) : "memory"); return v; }
__device__ __forceinline__ void sts128(uint32_t a, uint4 v) { asm volatile("st.shared.v4.u32 [%0], {%1,%2,%3,%4};" ::"r"(a), "r"(v.x), "r"(v.y), "r"(v.z), "r"(v.w) : "memory"); }

__device__ __forceinline__ void stg128(void* p, uint4 v) { asm volatile("st.global.v4.u32 [%0], {%1,%2,%3,%4};" ::"l"(p), "r"(v.x), "r"(v.y), "r"(v.z), "r"(v.w) : "memory"); }

__device__ __forceinline__ uint4 ldg128(const void* p) { uint4 v; asm volatile("ld.global.v4.u32 {%0,%1,%2,%3}, [%4];" : "=r"(v.x), "=r"(v.y), "=r"(v.z), "=r"(v.w) : "l"(p) : "memory"); return v; }
__device__ __forceinline__ uint2 ldg64(const void* p) { uint2 v; asm volatile("ld.global.v2.u32 {%0,%1}, [%2];" : "=r"(v.x), "=r"(v.y) : "l"(p) : "memory"); return v; }
__device__ __forceinline__ uint32_t ldg32(const void* p) { uint32_t v; asm volatile("ld.global.u32 %0, [%1];" : "=r"(v) : "l"(p) : "memory"); return v; }

__device__ __forceinline__ uint32_t pack2(float lo, float hi) {
    uint32_t r;
    asm("cvt.rn.bf16x2.f32 %0, %1, %2;" : "=r"(r) : "f"(hi), "f"(lo));
    return r;
}
__device__ __forceinline__ float bf_lo(uint32_t v) { return __uint_as_float(v << 16); }
__device__ __forceinline__ float bf_hi(uint32_t v) { return __uint_as_float(v & 0xFFFF0000u); }
__device__ __forceinline__ float rbf(float x) { return __uint_as_float(pack2(0.f, x) & 0xFFFF0000u); }
__device__ __forceinline__ float ex2(float x) { float r; asm("ex2.approx.ftz.f32 %0, %1;" : "=f"(r) : "f"(x)); return r; }

__device__ __forceinline__ float2 ln_finish(float sum, float sumsq) {
    const float m = sum * (1.0f / DM);
    const float v = fmaxf(fmaf(sumsq, 1.0f / DM, -m * m), 0.f);
    float s, r;
    asm("sqrt.approx.ftz.f32 %0, %1;" : "=f"(s) : "f"(rbf(rbf(v) + 1e-5f)));
    asm("rcp.approx.ftz.f32 %0, %1;" : "=f"(r) : "f"(rbf(s)));
    return make_float2(m, r);
}
__device__ __forceinline__ uint32_t ln_finish_packed(float sum, float sumsq) {
    const float m = sum * (1.0f / DM);
    const float v = fmaxf(fmaf(sumsq, 1.0f / DM, -m * m), 0.f);
    float s;
    asm("sqrt.approx.ftz.f32 %0, %1;" : "=f"(s) : "f"(rbf(rbf(v) + 1e-5f)));
    return pack2(s, m);
}
__device__ __forceinline__ float frsq(float x) { float r; asm("rsqrt.approx.ftz.f32 %0, %1;" : "=f"(r) : "f"(x)); return r; }
__device__ __forceinline__ float frcp(float x) { float r; asm("rcp.approx.ftz.f32 %0, %1;" : "=f"(r) : "f"(x)); return r; }
__device__ __forceinline__ bool elect_one() {
    uint32_t p;
    asm volatile("{\n.reg .pred p;\nelect.sync _|p, 0xffffffff;\nselp.u32 %0, 1, 0, p;\n}" : "=r"(p));
    return p != 0;
}
__device__ __forceinline__ void cluster_arrive_relaxed() { asm volatile("barrier.cluster.arrive.relaxed.aligned;" ::: "memory"); }
__device__ __forceinline__ void cluster_wait() { asm volatile("barrier.cluster.wait.aligned;" ::: "memory"); }
__device__ __forceinline__ unsigned long long ld_ll(const unsigned long long* p) {
    unsigned long long v;
    asm volatile("ld.relaxed.gpu.global.b64 %0, [%1];" : "=l"(v) : "l"(p) : "memory");
    return v;
}
__device__ __forceinline__ void st_ll(unsigned long long* p, uint32_t payload, uint32_t tag) {
    const unsigned long long v = (unsigned long long)payload | ((unsigned long long)tag << 32);
    asm volatile("st.relaxed.gpu.global.b64 [%0], %1;" ::"l"(p), "l"(v) : "memory");
}
__device__ __forceinline__ uint4 ld_ll4(const uint4* p) {
    uint4 v;
    asm volatile("{\n.reg .b128 t;\n.reg .b64 a, b;\nld.relaxed.gpu.global.b128 t, [%4];\nmov.b128 {a, b}, t;\nmov.b64 {%0, %1}, a;\nmov.b64 {%2, %3}, b;\n}"
                 : "=r"(v.x), "=r"(v.y), "=r"(v.z), "=r"(v.w) : "l"(p) : "memory");
    return v;
}
__device__ __forceinline__ void st_ll4(uint4* p, uint32_t x, uint32_t y, uint32_t z, uint32_t w) {
    asm volatile("{\n.reg .b128 t;\n.reg .b64 a, b;\nmov.b64 a, {%1, %2};\nmov.b64 b, {%3, %4};\nmov.b128 t, {a, b};\nst.relaxed.gpu.global.b128 [%0], t;\n}"
                 ::"l"(p), "r"(x), "r"(y), "r"(z), "r"(w) : "memory");
}

__device__ __forceinline__ void bulk_s2g(void* dst, uint32_t src, uint32_t bytes) {
    asm volatile("cp.async.bulk.global.shared::cta.bulk_group [%0], [%1], %2;" ::"l"(dst), "r"(src), "r"(bytes) : "memory");
}
__device__ __forceinline__ void bulk_commit() { asm volatile("cp.async.bulk.commit_group;" ::: "memory"); }
__device__ __forceinline__ void bulk_wait() { asm volatile("cp.async.bulk.wait_group 0;" ::: "memory"); }
__device__ __forceinline__ void fence_async_global() { asm volatile("fence.proxy.async.global;" ::: "memory"); }
__device__ __forceinline__ void fence_release() { asm volatile("fence.release.gpu;" ::: "memory"); }
__device__ __forceinline__ void fence_acquire() { asm volatile("fence.acquire.gpu;" ::: "memory"); }
__device__ __forceinline__ void ll_check5(uint4 (&f)[5], const uint4* p, uint32_t mark) {
#define LL_LD(i, a, b, c, d) "ld.relaxed.gpu.global.b128 q, [%20 + " #i "];\nmov.b128 {u, v}, q;\nmov.b64 {%" #a ", %" #b "}, u;\nmov.b64 {%" #c ", %" #d "}, v;\n"
    asm volatile("{\n.reg .pred p;\n.reg .b32 t, n, m;\n.reg .b128 q;\n.reg .b64 u, v;\nmov.u32 n, 0x7FFFF;\n"
                 "L:\nlop3.b32 t, %0, %4, %21, 0x7E;\nlop3.b32 t, t, %8, %21, 0xF6;\nlop3.b32 t, t, %12, %21, 0xF6;\nlop3.b32 t, t, %16, %21, 0xF6;\n"
                 "shr.u32 m, n, 18;\nand.b32 t, t, m;\nsetp.ne.u32 p, t, 0;\nvote.sync.any.pred p, p, 0xffffffff;\n@!p bra.uni D;\n"
                 LL_LD(0, 0, 1, 2, 3) LL_LD(512, 4, 5, 6, 7) LL_LD(1024, 8, 9, 10, 11) LL_LD(1536, 12, 13, 14, 15) LL_LD(2048, 16, 17, 18, 19)
                 "sub.u32 n, n, 1;\nbra.uni L;\nD:\n}"
                 : "+r"(f[0].x), "+r"(f[0].y), "+r"(f[0].z), "+r"(f[0].w), "+r"(f[1].x), "+r"(f[1].y), "+r"(f[1].z), "+r"(f[1].w), "+r"(f[2].x), "+r"(f[2].y),
                   "+r"(f[2].z), "+r"(f[2].w), "+r"(f[3].x), "+r"(f[3].y), "+r"(f[3].z), "+r"(f[3].w), "+r"(f[4].x), "+r"(f[4].y), "+r"(f[4].z), "+r"(f[4].w)
                 : "l"(p), "r"(mark) : "memory");
}
template<int TA, int TB>
__device__ __forceinline__ void wgmma_n192(float (&d)[96], uint64_t da, uint64_t db, int scale_d) {
  asm volatile("{\n.reg .pred p;\nsetp.ne.b32 p, %98, 0;\n"
    "wgmma.mma_async.sync.aligned.m64n192k16.f32.bf16.bf16 "
    "{%0, %1, %2, %3, %4, %5, %6, %7, %8, %9, %10, %11, %12, %13, %14, %15, %16, %17, %18, %19, %20, %21, %22, %23, %24, %25, %26, %27, %28, %29, %30, %31, %32, %33, %34, %35, %36, %37, %38, %39, %40, %41, %42, %43, %44, %45, %46, %47, %48, %49, %50, %51, %52, %53, %54, %55, %56, %57, %58, %59, %60, %61, %62, %63, %64, %65, %66, %67, %68, %69, %70, %71, %72, %73, %74, %75, %76, %77, %78, %79, %80, %81, %82, %83, %84, %85, %86, %87, %88, %89, %90, %91, %92, %93, %94, %95}, %96, %97, p, 1, 1, %99, %100;\n}\n"
    : "+f"(d[0]), "+f"(d[1]), "+f"(d[2]), "+f"(d[3]), "+f"(d[4]), "+f"(d[5]), "+f"(d[6]), "+f"(d[7]), "+f"(d[8]), "+f"(d[9]), "+f"(d[10]), "+f"(d[11]), "+f"(d[12]), "+f"(d[13]), "+f"(d[14]), "+f"(d[15]), "+f"(d[16]), "+f"(d[17]), "+f"(d[18]), "+f"(d[19]), "+f"(d[20]), "+f"(d[21]), "+f"(d[22]), "+f"(d[23]), "+f"(d[24]), "+f"(d[25]), "+f"(d[26]), "+f"(d[27]), "+f"(d[28]), "+f"(d[29]), "+f"(d[30]), "+f"(d[31]), "+f"(d[32]), "+f"(d[33]), "+f"(d[34]), "+f"(d[35]), "+f"(d[36]), "+f"(d[37]), "+f"(d[38]), "+f"(d[39]), "+f"(d[40]), "+f"(d[41]), "+f"(d[42]), "+f"(d[43]), "+f"(d[44]), "+f"(d[45]), "+f"(d[46]), "+f"(d[47]), "+f"(d[48]), "+f"(d[49]), "+f"(d[50]), "+f"(d[51]), "+f"(d[52]), "+f"(d[53]), "+f"(d[54]), "+f"(d[55]), "+f"(d[56]), "+f"(d[57]), "+f"(d[58]), "+f"(d[59]), "+f"(d[60]), "+f"(d[61]), "+f"(d[62]), "+f"(d[63]), "+f"(d[64]), "+f"(d[65]), "+f"(d[66]), "+f"(d[67]), "+f"(d[68]), "+f"(d[69]), "+f"(d[70]), "+f"(d[71]), "+f"(d[72]), "+f"(d[73]), "+f"(d[74]), "+f"(d[75]), "+f"(d[76]), "+f"(d[77]), "+f"(d[78]), "+f"(d[79]), "+f"(d[80]), "+f"(d[81]), "+f"(d[82]), "+f"(d[83]), "+f"(d[84]), "+f"(d[85]), "+f"(d[86]), "+f"(d[87]), "+f"(d[88]), "+f"(d[89]), "+f"(d[90]), "+f"(d[91]), "+f"(d[92]), "+f"(d[93]), "+f"(d[94]), "+f"(d[95])
    : "l"(da), "l"(db), "r"(scale_d), "n"(TA), "n"(TB));
}

template<int TA, int TB>
__device__ __forceinline__ void wgmma_n48(float (&d)[24], uint64_t da, uint64_t db, int scale_d) {
  asm volatile("{\n.reg .pred p;\nsetp.ne.b32 p, %26, 0;\n"
    "wgmma.mma_async.sync.aligned.m64n48k16.f32.bf16.bf16 "
    "{%0, %1, %2, %3, %4, %5, %6, %7, %8, %9, %10, %11, %12, %13, %14, %15, %16, %17, %18, %19, %20, %21, %22, %23}, %24, %25, p, 1, 1, %27, %28;\n}\n"
    : "+f"(d[0]), "+f"(d[1]), "+f"(d[2]), "+f"(d[3]), "+f"(d[4]), "+f"(d[5]), "+f"(d[6]), "+f"(d[7]), "+f"(d[8]), "+f"(d[9]), "+f"(d[10]), "+f"(d[11]), "+f"(d[12]), "+f"(d[13]), "+f"(d[14]), "+f"(d[15]), "+f"(d[16]), "+f"(d[17]), "+f"(d[18]), "+f"(d[19]), "+f"(d[20]), "+f"(d[21]), "+f"(d[22]), "+f"(d[23])
    : "l"(da), "l"(db), "r"(scale_d), "n"(TA), "n"(TB));
}

__device__ __forceinline__ void wgmma_rs80(float (&d)[40], const uint4& a, uint64_t db, int scale_d) {
  asm volatile("{\n.reg .pred p;\nsetp.ne.b32 p, %45, 0;\n"
    "wgmma.mma_async.sync.aligned.m64n80k16.f32.bf16.bf16 {%0,%1,%2,%3,%4,%5,%6,%7,%8,%9,%10,%11,%12,%13,%14,%15,%16,%17,%18,%19,%20,%21,%22,%23,%24,%25,%26,%27,%28,%29,%30,%31,%32,%33,%34,%35,%36,%37,%38,%39}, {%40,%41,%42,%43}, %44, p, 1, 1, 1;\n}\n"
    : "+f"(d[0]), "+f"(d[1]), "+f"(d[2]), "+f"(d[3]), "+f"(d[4]), "+f"(d[5]), "+f"(d[6]), "+f"(d[7]), "+f"(d[8]), "+f"(d[9]), "+f"(d[10]), "+f"(d[11]), "+f"(d[12]), "+f"(d[13]), "+f"(d[14]), "+f"(d[15]), "+f"(d[16]), "+f"(d[17]), "+f"(d[18]), "+f"(d[19]), "+f"(d[20]), "+f"(d[21]), "+f"(d[22]), "+f"(d[23]), "+f"(d[24]), "+f"(d[25]), "+f"(d[26]), "+f"(d[27]), "+f"(d[28]), "+f"(d[29]), "+f"(d[30]), "+f"(d[31]), "+f"(d[32]), "+f"(d[33]), "+f"(d[34]), "+f"(d[35]), "+f"(d[36]), "+f"(d[37]), "+f"(d[38]), "+f"(d[39])
    : "r"(a.x), "r"(a.y), "r"(a.z), "r"(a.w), "l"(db), "r"(scale_d));
}

__device__ __forceinline__ void wgmma_ss80(float (&d)[40], uint64_t da, uint64_t db) {
  asm volatile("wgmma.mma_async.sync.aligned.m64n80k16.f32.bf16.bf16 {%0,%1,%2,%3,%4,%5,%6,%7,%8,%9,%10,%11,%12,%13,%14,%15,%16,%17,%18,%19,%20,%21,%22,%23,%24,%25,%26,%27,%28,%29,%30,%31,%32,%33,%34,%35,%36,%37,%38,%39}, %40, %41, 1, 1, 1, 0, 1;"
    : "+f"(d[0]), "+f"(d[1]), "+f"(d[2]), "+f"(d[3]), "+f"(d[4]), "+f"(d[5]), "+f"(d[6]), "+f"(d[7]), "+f"(d[8]), "+f"(d[9]), "+f"(d[10]), "+f"(d[11]), "+f"(d[12]), "+f"(d[13]), "+f"(d[14]), "+f"(d[15]), "+f"(d[16]), "+f"(d[17]), "+f"(d[18]), "+f"(d[19]), "+f"(d[20]), "+f"(d[21]), "+f"(d[22]), "+f"(d[23]), "+f"(d[24]), "+f"(d[25]), "+f"(d[26]), "+f"(d[27]), "+f"(d[28]), "+f"(d[29]), "+f"(d[30]), "+f"(d[31]), "+f"(d[32]), "+f"(d[33]), "+f"(d[34]), "+f"(d[35]), "+f"(d[36]), "+f"(d[37]), "+f"(d[38]), "+f"(d[39])
    : "l"(da), "l"(db));
}

__device__ const __align__(1024) uint32_t c_fft[11264] = {
0x2ddc2dba,0x2fe62eb5,0x2ed02eb5,0xafffaf6e,0x2e1f2dfe,0x2e3f2fbc,0x2f022ee9,0xad27af30,0x2e5e2e3f,0x1fd92b5e,0x2f302f1a,0x244ea875,0x2e992e7c,0xad96a993,0x2f5a2f46,0x2e992c32,
0xad00ad72,0xa17eac32,0xa17ea515,0xabb79cb6,0xac07ac87,0x2dfe29f1,0x1fd99648,0xafedae99,0xa9f1ab05,0x2fd42fbc,0x26a1244e,0xad96af91,0xa765a8d5,0x2aaa2e3f,0x29932875,0x2515a8d5,
0xae99adfe,0xb000aee9,0xaf6eafbc,0x2c872f30,0xaf80af1a,0xac32af02,0xae7caf02,0xaaaa217e,0xaff4afc9,0x2b5e9cb6,0xad27addc,0xaff4ae7c,0xafedb000,0x2ffc2eb5,0xab05ac5d,0xacd8af5a,
0x2c072d27,0x9fd92bb7,0xadfead00,0x2fed2e1f,0x25db2993,0xaf6eacb0,0xaf6eaed0,0x2c5d2f46,0xa5151648,0xaddcafdd,0xafffafd4,0xac321648,0xabb7a934,0x28d5a814,0xafa0afed,0xaff4af30,
0x2f302e3f,0x2fed2f1a,0x28142b5e,0x2934a875,0x30002fc9,0x26a12ddc,0xa5db1cb6,0x30002e7c,0x2f462fd4,0xaed0aa4e,0xacb0aa4e,0x29932e99,0x2d272e5e,0xae3faffc,0xaf02adfe,0xae1fa814,
0xa9f1acd8,0x26a1ab05,0x2fd42ffc,0xad96afed,0x2515a30e,0x2fff2e1f,0x2ddc2f1a,0x2c32a30e,0x2d272aaa,0x28752e7c,0x28752c32,0x2fa02f80,0x2f912e99,0xaee9a9f1,0xa8141648,0x9fd92c87,
0xafa0ae7c,0xafafaf46,0x2d002993,0xafa0ac32,0xaf91b000,0x244eac5d,0x2fbc2eb5,0xab05af5a,0xac87ae5e,0x30002dfe,0x2f6e2ffc,0x2e992814,0x1cb6a875,0x25152e1f,0x2c322e1f,0x2d722ff4,
0x27652c87,0xa9932a4e,0xaaaaadba,0xa5152c87,0xabb7a44e,0xafa0af30,0x28d59fd9,0xaff4ae5e,0xaf91ae1f,0x2814abb7,0x2ee92d00,0x1fd9ad27,0xaf5aafff,0x2fd42ed0,0x2fd42fe6,0x30002ddc,
0x2f462f6e,0x2c322fdd,0x2e7c2fdd,0xa993b000,0xab5e2934,0xafafacd8,0xad00244e,0x2f1a2dfe,0xaee9afaf,0x2f30a17e,0xadfeaff8,0xafbca30e,0x2c5da765,0xa9f12ddc,0x2d969cb6,0x2c5dacb0,
0x2bb7a993,0x2f1aa515,0x2f1a2765,0xaff4aaaa,0x2e5e2fd4,0xab052dba,0x29342f6e,0x2ee9a6a1,0xadba1fd9,0xa5dbafed,0xafddac07,0xaa4e2dfe,0xacb0aff8,0x2ddc2f02,0x9cb6ae3f,0xa765aff8,
0xaeb5af91,0xaa4eafed,0x9648ae5e,0xac5d2d4d,0x2ddca17e,0x2e7c2e3f,0x2fc92e3f,0x1cb6afa0,0x2bb72fe6,0xaff8a993,0xab5e2aaa,0x2bb72fc9,0xafbcaa4e,0x2f30a5db,0xadfeafdd,0xaee9adba,
0xacd828d5,0xaf91230e,0xaf30af02,0x2c072fa0,0xac5dafff,0x2dbaac32,0x2dbaa515,0xae99addc,0x2fc929f1,0xa9932eb5,0x2aaa2fdd,0x2fe629f1,0xa30e2dfe,0xa17eafed,0xaff8ac07,0xafaf1fd9,
0x2dfe2faf,0x28142ff8,0xae5e217e,0x2ffc230e,0xaf5aa515,0xac87af46,0xa6a1af80,0xaf5a2765,0x1cb6ae99,0x2e7c2dba,0x2fc92dba,0x2ddcac5d,0x2f1a2ee9,0xafafab05,0xad002934,0xab5e2e5e,
0x2dbaa814,0x2fdd9fd9,0x25db2f91,0x2a4eaee9,0x27652faf,0xaf4628d5,0xaf80ae1f,0xa5152faf,0xafa0addc,0x2e3fac32,0x2e3fa515,0xa17eafff,0x2dfea6a1,0xacd82dba,0x244e2f6e,0x29342fd4,
0xad27afc9,0xa30eafff,0x2faf2d72,0xad27ae7c,0x2ffc2a4e,0x28142fdd,0xae5e25db,0x2dfe2dba,0xac5d2c07,0xaa4eaf91,0x9648af30,0xaeb5acd8,0xa993aff4,0x2c322f1a,0x2e7c2f1a,0x2f462bb7,
0xae7c26a1,0xafff1648,0x2d72aa4e,0xafc926a1,0x230eaee9,0x2ff89fd9,0x217e2f91,0x2fafa814,0x2d4d2fa0,0xafed230e,0xae5eaf02,0xaf9128d5,0xb000aaaa,0x2fdda515,0x2fdd2765,0x2f6ea993,
0x9cb63000,0xacb02fd4,0xa7652fd4,0x2ddcaf5a,0x217eaffc,0x2ff4ac07,0x2875afbc,0xaff82934,0xa44e2ff4,0xadfea8d5,0xa9342fa0,0x2cd82bb7,0x25dbafe6,0x16482f46,0x29f1af80,0x25dbafc9,
0x2ff41cb6,0x2e1f2765,0x2e1f2cb0,0xa875addc,0xafbca5db,0x1fd9af5a,0xad4dad96,0xacd82fdd,0x2f5a2934,0xaeb52ee9,0x2c5d2e5e,0x3000ab05,0xaed0ab5e,0x2f80a30e,0xaaaaaf02,0xacb0ab5e,
0x25dbaffc,0x2d96afbc,0x2f5aac07,0xafdd2934,0xaaaa2fa0,0xafc92875,0xafe62875,0x29932d27,0x2d00aed0,0x28d52d72,0x2ff89cb6,0x2d00afe6,0xae5e2d96,0x2d4dafd4,0xaf91a6a1,0xafed29f1,
0xafbca17e,0xad4da875,0x1fd9aff4,0xacd82ff8,0x2e992aaa,0xaa4e2fe6,0xaa4e2fc9,0x2fd4a993,0xacb0ad96,0x2fffac87,0x2d72aeb5,0xa765ad96,0x28752f30,0xab5eac07,0xaf1a2cd8,0xae3f2f91,
0xa9342ff4,0xae5e2fa0,0xaee9a8d5,0x2b052bb7,0x2d96aed0,0x2eb59cb6,0x2c872d72,0x2d96afe6,0xaf802c5d,0x2765af6e,0xa515af6e,0xaf4625db,0x2ff8a44e,0xaff42d4d,0xa8752ffc,0xa17e2ee9,
0x2f5a244e,0x2c5d2934,0xaeb52dfe,0x3000acd8,0xacb0ad00,0x2d72aff8,0x2fffa8d5,0xa765ad00,0x217e2f80,0xaf022515,0xaf02a765,0xaf1a2f46,0x2b05afdd,0xa8142f5a,0x2c072d96,0x2d4d25db,
0x2b5eafe6,0x2f02af80,0x230e2f46,0x2b5eafc9,0xaf302d96,0xacd8a6a1,0x2c07afd4,0xaf9129f1,0x2fdda44e,0xad962ffc,0xaf5a2d4d,0xa5db2ee9,0xad72abb7,0x2e7ca17e,0x2fc9a17e,0x2fffad00,
0xaed0a5db,0xaaaaa9f1,0x2f809648,0xacb0a5db,0x28752e5e,0xaf1a2f91,0xab5ead4d,0xae3f2fed,0x2b05aff8,0x2c072875,0xa8142ff4,0x2d4d217e,0xaf6e2d72,0x2eb5afc9,0x2eb5ae7c,0x2dbaafff,
0xaf802f5a,0xafc92e99,0xafe62e99,0x2f46ad96,0x28d52b05,0xaf022fed,0x230e2cd8,0x2fa0affc,0x2fbcaf02,0xa9342d27,0x2ffcae1f,0x2c07ae3f,0xa6a1ac32,0x2a4e9cb6,0x9648ad72,0xa6a1a515,
0x28752aaa,0xa8d52cb0,0xa8d52ed0,0x2e3faf80,0x2fedaeb5,0x29349648,0x2f30aa4e,0x2814ac5d,0x1648ad4d,0x2e99acd8,0x2c87afbc,0xa9f11fd9,0xafe62d27,0x2fffafaf,0xaddc230e,0xaed02d27,
0x2fd4af30,0x2f6eae5e,0x2dbaa44e,0xa6a19fd9,0x1cb6ad27,0x2fe6aff4,0x2ed0aff4,0xad722b5e,0xafaf2cb0,0x2e1faf46,0xa8d5a993,0xafaf2ed0,0xac072f6e,0x2934ac87,0xaffc2e99,0xafbc3000,
0xa44eab5e,0x2b05ad00,0x2f91afaf,0xafbc2f1a,0xafd42d72,0x1648a765,0x1648acb0,0xafdd2fff,0xac322f5a,0xaaaa26a1,0xaf802c87,0xae7c2f5a,0x2d009fd9,0xae1f2cd8,0xad272fbc,0xabb72d4d,
0xaffc2f02,0xaee92e1f,0x244ead27,0xad4d2e3f,0xa9f12e7c,0xafdd2f80,0xaeb52aaa,0xa9f12c32,0x2d72a5db,0xafe63000,0xaed03000,0x9cb626a1,0x2fa0afbc,0xaf022f91,0x230e2b05,0x28d5a44e,
0x96482c07,0xac872d4d,0xae992b05,0x29f1a814,0x2ed0abb7,0xa9932b5e,0xaf462ff8,0x2cb0abb7,0x2f1aafff,0xa30e2765,0xa30e2cb0,0x2e1fad72,0x1fd9ac5d,0x244e9648,0x2e5eaa4e,0x2f30aeb5,
0x2ff8aed0,0x2e3faddc,0xaf022fff,0x2ff8afe6,0x2d4daf6e,0x2ee9ae99,0xa44e2c87,0x2ffcb000,0xa6a1a814,0x2f6eaf30,0x2dbaa934,0x2fd4afed,0xaf462d00,0x2fc9afa0,0x2fe6afa0,0x2f80afaf,
0x2515ac5d,0x2d72ad96,0x1cb629f1,0x2c32ac5d,0xad002814,0x2d27ad4d,0x2e1fab05,0x2bb7ac07,0xaffc2f1a,0x2cd8ad00,0x2fedafaf,0x2b05ab5e,0xadba2f80,0x2c87acb0,0x2c87aed0,0x2a4eaaaa,
0x2f802f6e,0x2fc92fdd,0x2fe62fdd,0xaf46b000,0x2fa02f91,0x2bb72e5e,0x2ff42fed,0xa8d5ad4d,0x2fbc2faf,0xa934217e,0x2ffc2ff8,0x2c07230e,0x2fd42fc9,0xaf5aad72,0x30002fff,0x2fd42e7c,
0x2bb72aaa,0x2f1a2cb0,0x2f1a2ed0,0xaff4af80,0x2cd82c5d,0x2f303000,0x2f912f5a,0xac07aeb5,0x2dba2d4d,0x25db2cd8,0x2fdd2fbc,0x2a4e9fd9,0x2e7c2e1f,0xad72a875,0x2fff2ff4,0x2fc92e1f,
0xa6a1a934,0x29f1a44e,0x2d962cd8,0xafd4adfe,0x1cb6a17e,0x2fe62e3f,0x2ed02e3f,0xad72afa0,0x28752515,0x2d272f80,0x2fa02f46,0x2875a765,0x2c072a4e,0xa93425db,0x2ffc2fdd,0x2fbc2dba,
0xae5eaf1a,0xa934ae3f,0x2b052875,0xaee9ab5e,0xac5dad72,0x2dba2765,0x2dba2cb0,0xae99afff,0xa765aa4e,0x2f802fd4,0x2f462e99,0x2515aa4e,0x230e9fd9,0x217e2cd8,0x2ff82fbc,0x2faf2d4d,
0xaffcafaf,0xaee9aff8,0x244ea17e,0xad4da30e,0xaf6eafe6,0x25dbaaaa,0x2c5d2993,0xaf6eafc9,0xad72ae99,0x2fe62dba,0x2ed02dba,0x1cb6ac5d,0xa8d5ac07,0x2bb72f30,0x2ff42f91,0x2fa02cd8,
0xadbaac07,0xafddad4d,0xa5dbab05,0xaa4e2814,0xafc9af02,0xaaaaaf1a,0x2993217e,0xafe6af02,0xafa0afff,0x2e3f2765,0x2e3f2cb0,0xa17ead72,0xad4daeb5,0x2e5e3000,0x2fed2f5a,0x2f912c5d,
0xa17e2765,0xad001cb6,0xabb7addc,0xa17e2cb0,0xad4daa4e,0xaee9afdd,0x244ea5db,0xaffcadba,0xafd4aee9,0x29f1a934,0x2d962b05,0xa6a1ae5e,0xaf46aff4,0x2fc92f1a,0x2fe62f1a,0x2f802bb7,
0x2cb02eb5,0x1cb62dba,0xaddcaf6e,0x27652eb5,0xa30e2814,0xaff8ad4d,0xa17eab05,0xafafac07,0xadfeab5e,0xa44eae3f,0x2cd82875,0xa934af1a,0xb000af80,0x2fdd2cb0,0x2fdd2ed0,0x2f6e2aaa,
0x2d723000,0x25152fd4,0x2c322fd4,0x1cb6af5a,0xae1f9fd9,0xae3faee9,0xaf02a814,0x2d272f91,0xacd8aff4,0x2ffc28d5,0xab05afa0,0xafedabb7,0x2e992515,0xad962aaa,0x2f5a2993,0x2e99a765,
0x2ff42ddc,0x2e1f2ed0,0x2e1f2fe6,0xa875afff,0xa8142c87,0xaffca9f1,0xadfe1648,0x2e5e2e99,0xaf5aaf30,0x2eb5a814,0xac5dafed,0xb000a934,0x2c32a8d5,0xa9932e3f,0x2f462875,0x2e7ca8d5,
0x2e991fd9,0x30002814,0x2f6e2ee9,0xac87af91,0x29932fa0,0xaed02875,0xacb02875,0x2f462d27,0xaff4ac32,0x2b5eaddc,0xad27afff,0xaff4a515,0x244ead96,0x1fd92fd4,0x2f3026a1,0x2e5ea9f1,
0x2814ad27,0x2dfeabb7,0x2ffc2d00,0xae5eae1f,0x2e992f80,0xaa4e2e7c,0xaa4e2c32,0x2fd42aaa,0xae7c1648,0x9cb6afdd,0xaddcafd4,0xafc91648,0xa875af91,0x2b5e2fbc,0x2f1a244e,0x2e3fab05,
0xab05aff4,0x244eafa0,0x2fbc28d5,0xaf91abb7,0x30002c32,0x26a12fff,0xa5db2ddc,0x30002515,0xaaaa2c5d,0xac32af6e,0xae7caf6e,0xaf8025db,0xad27afed,0x2e3f2dfe,0x2f021fd9,0x2e1fac07,
0xaf5aae5e,0xac5daf30,0x2eb59fd9,0xb000a44e,0x2e7ca30e,0x2ddc2e1f,0x1cb62f1a,0x2fc9a30e,0x217e2f46,0xaf02acb0,0xaf02aed0,0xaf1a2993,0xaf30ae99,0x2fbc29f1,0x2ee99648,0x2dfeac87,
0xafa0a515,0xafafa993,0x2d00aaaa,0xafa02765,0x2934ad96,0x2fed26a1,0x28142fd4,0x2f30a9f1,0x2c872fed,0xb0009fd9,0xaf6eadfe,0xae992c07,0xafffabb7,0x2fe6a17e,0x2ed0a17e,0x2ddcad00,
0xac322c87,0xaf462a4e,0x2993adba,0xae7c2c87,0xa875afed,0x2f1aab05,0x2b5e2ffc,0x2e3facd8,0x2f302e1f,0xaee92bb7,0xafbcad00,0xadfe2d27,0xaf6e9cb6,0x2eb5ac32,0x2eb5a515,0x2dbaad72,
0xaaaa2f5a,0xaed02e99,0xacb02e99,0x2f80ad96,0x2b5eaf30,0x2fafa44e,0x2d00ae5e,0xaf1a9fd9,0xac072f02,0xab05ad27,0xad4d2e1f,0x28142e3f,0x2c5daed0,0xa9f12fff,0x2d96addc,0x2c5dafe6,
0x28752f80,0xa8d52fe6,0xa8d52fc9,0x2e3faf46,0xa44eafd4,0x2f91adba,0x2b05af6e,0xafbc26a1,0x96482ffc,0xae99a44e,0xac872ee9,0x29f12d4d,0x2515aff8,0x1cb62f02,0x2d72ae3f,0x2c32aff8,
0x2eb52b05,0x2a4e2cd8,0x16482fed,0x2c5daffc,0xad72ad27,0x2cb0aff4,0x2765aff4,0xafff2b5e,0x2bb72e7c,0xaff82aaa,0xab5e2f80,0x2bb72c32,0xa814af6e,0x2b052c87,0x2d4dae99,0x2c07b000,
0x2feda8d5,0x2f30a30e,0x29342f02,0x2814afa0,0xafd49cb6,0x1648aed0,0x1648afe6,0xafdd2d72,0x2ed029f1,0xaf462eb5,0xa9932fdd,0x2cb029f1,0xad00ad4d,0x2e1f244e,0x2d27aee9,0x2bb7affc,
0x2d4daf02,0x2fbcae1f,0x2cd82d27,0x9fd9ae3f,0xaf5a2cb0,0xac87a993,0xa6a1af46,0xaf5a2ed0,0x2fffa5db,0xacb03000,0xa7653000,0x2d7226a1,0xaf1aa814,0x2fafa934,0x2d00af30,0x2b5eafed,
0x1648afbc,0x2c87affc,0x2e992934,0xa9f1ac07,0xac322faf,0xaf8028d5,0xaaaaae1f,0xae7c2faf,0x2f1aad72,0xa30e2ed0,0xa30e2fe6,0x2e1f1cb6,0xaffc26a1,0x2fedadba,0x2cd8af6e,0x2b05afd4,
0xad27ac32,0xa30ead72,0x2faf9cb6,0xad27a515,0x1fd92f6e,0xafbc2e99,0xacd8ac87,0xad4d3000,0x2c5dafbc,0x2a4e2b05,0x16482f91,0x2eb5a44e,0xaf802d00,0x2ed0afa0,0x2cb0afa0,0x2aaaafaf,
0xafe626a1,0xaddc1648,0x2fffaa4e,0xaed026a1,0x2d002c07,0xad272ffc,0xae1fa934,0xabb72fbc,0x1fd9afa0,0x2e5ea30e,0x244e2f02,0x2f30a8d5,0xadba2f46,0x2c87afe6,0x2c87afc9,0x2a4eaf80,
0xafff2d96,0xae7c2c5d,0xafc92c5d,0x2d72a9f1,0xa17e2dfe,0xaff42fbc,0xa8752ee9,0x2ff8af30,0x2fedad00,0xad4d2f1a,0x2f91ab5e,0x2e5eafaf,0x25dbae7c,0x16482993,0x29f1af46,0x25dbac32,
0xae3f2fff,0xaff82fc9,0xaff82e7c,0x2f02ad72,0x2c0725db,0xadfe2f5a,0x9fd92d96,0x2fedafdd,0x2f6eaf91,0xa6a12c07,0x2fd4acd8,0x2dbaaf30,0xa765ab5e,0x2aaaa30e,0x2993af02,0x2515ab5e,
0xa5db2dfe,0xad962ee9,0xaf5a2fbc,0x2fddaf30,0x2f46ab5e,0xa7652bb7,0x25152bb7,0x2f80aff8,0x2d00afc9,0x28d59cb6,0x2ff8addc,0x2d00ae7c,0xacd89648,0x2dfeac5d,0x2934aeb5,0x244eaa4e,
0x2c07217e,0x9fd92875,0xadfe2ff4,0x2fedaff8,0x2fddaf46,0x29f1a515,0x29f12765,0x2eb5af80,0x2515ad96,0x2ddcac87,0x2fffaeb5,0x2c32ad96,0xaf022b05,0x2fa0aee9,0x28d5ae5e,0x230ea934,
0x2f91ad00,0x2cd8ab5e,0xac072f1a,0x2f30afaf,0x2d96afc9,0x2eb5addc,0x2c879cb6,0x2d96ae7c,0xa993a6a1,0x2fc9af5a,0x2fe6af5a,0x2aaaac87,0xaff82e5e,0x2ff4affc,0x2875adfe,0x217ea814,
0x2f6eafed,0x2fd4af91,0xa6a12d4d,0x2dbaae5e,0x2515ad00,0x2fffaff8,0x2ddca8d5,0x2c32ad00,0xae1f2993,0x2fafafe6,0x2fafafc9,0x28d5aaaa,0xaf912fdd,0x2ee9af5a,0x2814ad96,0x1fd9a5db,
0x2b5eae7c,0x2f02af46,0x230e2993,0x2b5eac32,0xab059648,0x2e5eaeb5,0x2ee9ac5d,0x2934aa4e,0xafdd2e5e,0x2d96adfe,0x2f5aaffc,0x25dba814,0xaddc2faf,0x2cb0ad27,0x2765ad27,0x1cb6a30e,
0xa765a5db,0x2993a9f1,0x2aaa9648,0x2515a5db,0xaf022cd8,0x28d5a934,0x2fa0adfe,0x230ea44e,0xaf912ff8,0x2814a875,0x2ee9aff4,0x1fd9a17e,0xaa4e2ddc,0x26a1a765,0x26a1acb0,0x16489cb6,
0x2d722d96,0x25152c5d,0x2c322c5d,0x1cb6a9f1,0x2d272d4d,0xad00a814,0x2bb72c07,0x2e1f2b05,0x2cd82d00,0xaffcaf1a,0x2b052b5e,0x2fed2faf,0x2c872cb0,0xadbaaf80,0x2a4e2aaa,0x2c872ed0,
0x2e3f2ddc,0x2ff82ed0,0x2ff82fe6,0xaf02afff,0x2ee92e99,0x2d4d2f6e,0x2ffc3000,0xa44eac87,0x2f6e2f30,0xa6a12814,0x2fd42fed,0x2dba2934,0x2fc92fa0,0xaf46ad00,0x2f802faf,0x2fe62fa0,
0xac87ad4d,0x9648ac07,0x29f12814,0xae99ab05,0xa993ab5e,0x2ed02bb7,0x2cb02bb7,0xaf46aff8,0xa30ea765,0x2f1a2fff,0x2e1f2d72,0xa30eacb0,0x244e1648,0x1fd92c5d,0x2f302eb5,0x2e5e2a4e,
0xaee9ae1f,0xaffcaf02,0xad4dae3f,0x244e2d27,0xafddaf80,0xa9f1ae7c,0xa9f1ac32,0xaeb5aaaa,0xafe6b000,0x2d7225db,0x9cb6a6a1,0xaed0b000,0xaf02af91,0x2fa02fbc,0x28d5244e,0x230eab05,
0x2b052d00,0xa44e2b5e,0xafbcaf1a,0x2f912faf,0x16482765,0xafd4ad72,0xafddafff,0x16482cb0,0xaaaaa6a1,0xac32af5a,0xae7caf5a,0xaf80ac87,0xae1facd8,0x2d001fd9,0xabb7ad4d,0xad27afbc,
0x2f6e2e5e,0x2fd42f30,0xa6a11fd9,0x2dba244e,0x2fe62ff4,0x1cb62d27,0xad72ab5e,0x2ed02ff4,0x2e1f2f46,0xafafacb0,0xafafaed0,0xa8d52993,0x29342c87,0xac07af6e,0xafbcb000,0xaffcae99,
0xa8d5acb0,0x2875aaaa,0x2e3f2f80,0xa8d5aed0,0x29341648,0x2fed2eb5,0x28142c5d,0x2f302a4e,0x2e992cd8,0x16482d4d,0xa9f19fd9,0x2c872fbc,0x2fff2faf,0xafe6ad27,0xaed0ad27,0xaddca30e,
0xafc9ae99,0xaf80af5a,0x2f462d96,0xafe6ae99,0xaf02afed,0x28d5ab05,0x2fa02ffc,0x230eacd8,0xa934ad27,0x2fbc2f02,0x2c072e3f,0x2ffc2e1f,0x2a4e1cb6,0xa6a12c32,0xa6a12515,0x96482d72,
0xaaaa29f1,0xaed025db,0xacb025db,0x2f801648,0xaf1aaf91,0x2875ae5e,0xae3fafed,0xab5e2d4d,0x2c07a875,0x2b052ff8,0x2d4da17e,0xa814aff4,0x2eb52fc9,0xaf6ead72,0x2dba2fff,0x2eb52e7c,
0x2f022f80,0x2b5e2fe6,0x2b5e2fc9,0x230eaf46,0xacd826a1,0xaf30ad96,0xaf91a9f1,0x2c072fd4,0xad96affc,0x2fdd244e,0xa5dbaee9,0xaf5aad4d,0x2e7c217e,0xad722bb7,0x2fff2d00,0x2fc9217e,
0x2c5da934,0x2f5aa44e,0x30002cd8,0xaeb5adfe,0x2d722ff8,0xacb02d00,0xa7652d00,0x2fff28d5,0xaf02a515,0x217eaf80,0xaf1aaf46,0xaf022765,0xa814af5a,0x2b052fdd,0x2d4da5db,0x2c07ad96,
0xae5eafa0,0xa934aff4,0x2b05abb7,0xaee928d5,0x2eb51cb6,0x2d962ed0,0x2d962fe6,0x2c87ad72,0x27652f6e,0xaf80ac5d,0xaf46a5db,0xa5152f6e,0xaff4ad4d,0x2ff8244e,0xa17eaee9,0xa875affc,
0xad4d2875,0xafbc217e,0xacd8aff8,0x1fd92ff4,0xaa4eafe6,0x2e99aaaa,0x2fd42993,0xaa4eafc9,0x2fff2c87,0xacb02d96,0xa7652d96,0x2d722eb5,0xab5e2c07,0x2875af30,0xae3faf91,0xaf1aacd8,
0x2d962fbc,0x25db2ffc,0xafdda934,0x2f5a2c07,0xafc9a875,0xaaaaafa0,0x2993ad27,0xafe6a875,0x28d5ad72,0x2d002ed0,0x2d002fe6,0x2ff81cb6,0x2d4d2fd4,0xae5ead96,0xafeda9f1,0xaf9126a1,
0x2e1fa765,0x2ff49cb6,0xa8752ddc,0x2e1facb0,0x1fd92f5a,0xafbc25db,0xacd8afdd,0xad4d2d96,0xaeb5aee9,0x2f5aa934,0x30002b05,0x2c5dae5e,0x2f80230e,0xaed02b5e,0xacb02b5e,0xaaaa2f02,
0xacb0afd4,0x9cb6b000,0x2ddc2f5a,0xa765afd4,0x2ff42c07,0x217e2ffc,0xaff8a934,0x28752fbc,0xadfe28d5,0xa44eaff4,0x2cd8abb7,0xa934afa0,0x1648af46,0x25db2fe6,0x25db2fc9,0x29f12f80,
0xafff9648,0xae7ca6a1,0xafc9a6a1,0x2d722a4e,0x2ff81fd9,0x230e2ee9,0x2faf2814,0x217eaf91,0xafeda30e,0x2d4dafa0,0xaf91a8d5,0xae5e2f02,0x2fdd2515,0xb0002aaa,0x2f6e2993,0x2fdda765,
0xa30e2fff,0xad272fc9,0xad272e7c,0x2fafad72,0x2814afdd,0x2ffcaa4e,0x2dfeadba,0xae5ea5db,0xaa4e2f91,0xac5dac07,0xaeb52cd8,0x96482f30,0x2c32af1a,0xa9932ff4,0x2f46abb7,0x2e7caf1a,
0x2fdd1fd9,0x2dba2814,0x2a4e2ee9,0x25dbaf91,0xaf46a8d5,0x2765afaf,0xa515afaf,0xaf802e1f,0x2e3f2c32,0xafa02ddc,0xa17e2fff,0x2e3f2515,0xacd8adba,0x2dfe26a1,0x2934afd4,0x244eaf6e,
0x2814aff8,0x2dfeafaf,0x2ffca30e,0xae5ea17e,0xac872f46,0xaf5a2515,0xaf5aa765,0xa6a12f80,0x2e7cadba,0x1cb62e99,0x2ddc2c5d,0x2fc9adba,0xafaf2b05,0x2f1aaee9,0xab5eae5e,0xad00a934,
0xaf91a30e,0xacd8a8d5,0x2c07afa0,0xaf302f02,0x2dba2c32,0xac5d2fff,0xae992ddc,0x2dba2515,0xa993aeb5,0x2fc9a9f1,0x2fe6a9f1,0x2aaaafdd,0xa17e2fed,0xa30eadfe,0xafaf9fd9,0xaff82c07,
0xaa4e2fed,0xaeb52f91,0xac5dad4d,0x96482e5e,0x2e7cae3f,0x2ddc217e,0x1cb62fa0,0x2fc9ae3f,0xaff82993,0x2bb7afe6,0x2bb7afc9,0xab5eaaaa,0x2f3025db,0xafbc2a4e,0xaee92dba,0xadfe2fdd,
0x2f1a2515,0x2bb72993,0xaff42aaa,0x2f1aa765,0xab05adba,0x2e5eafd4,0x2ee926a1,0x2934af6e,0xa5db2fed,0xadba9fd9,0xaa4eadfe,0xafdd2c07,0x2ddcaf02,0xacb02ff8,0xa7652ff8,0x9cb62e3f,
0x2c32afdd,0x2f46af6e,0xa9933000,0x2e7cafdd,0xafaf2cd8,0xab5ea934,0x2f1aadfe,0xad00a44e,0x2f30217e,0xaee92faf,0xafbc230e,0xadfe2ff8,0xa9f1addc,0x2c5d2765,0x2c5d2cb0,0x2d961cb6,
0xa993aa4e,0x2765ac87,0xa515ac87,0xaaaa2dba,0xafa02f30,0xabb7244e,0xaff42e5e,0x28d51fd9,0x28142bb7,0xaf912e1f,0x1fd92d27,0x2ee9ad00,0x2fd4aed0,0xaf5a2fff,0x3000addc,0x2fd4afe6,
0xafaf2f46,0xafa02e7c,0xafa02c32,0x2d00a993,0x244e2c5d,0xaf913000,0xab052f5a,0x2fbcaeb5,0x3000adfe,0xac872e5e,0x2e99a814,0x2f6eaffc,0x2515ae1f,0x1cb62875,0x2d72aff4,0x2c32ae1f,
0x26a12b05,0xa9f12cd8,0xad962fed,0x2fd4affc,0x2fffae1f,0x2515230e,0x2c32230e,0x2ddcaf1a,0x2875ae7c,0x2d27aaaa,0x2fa0af80,0x2875ac32,0xaee929f1,0x2f91ae99,0x9fd9ac87,0xa8149648,
0x2fedaf1a,0x2f30ae3f,0x29342875,0x2814ab5e,0x26a1addc,0x3000afc9,0x3000ae7c,0xa5db9cb6,0xaed02a4e,0x2f46afd4,0x2993ae99,0xacb02a4e,0xae3f2ffc,0x2d27ae5e,0xae1f2814,0xaf022dfe,
0x9fd9abb7,0x2c07ad27,0x2fedae1f,0xadfe2d00,0xaf6e2cb0,0x25dba993,0x2c5daf46,0xaf6e2ed0,0xaddc2fdd,0xa5159648,0xac329648,0xafff2fd4,0x28d52814,0xabb72934,0xaff42f30,0xafa02fed,
0xb0002ee9,0xae992dfe,0x2c87af30,0xaf6e2fbc,0xac322f02,0xaf802f1a,0xaaaaa17e,0xae7c2f02,0x2b5e1cb6,0xaff42fc9,0xaff42e7c,0xad272ddc,0x2ffcaeb5,0xafed3000,0xacd82f5a,0xab052c5d,
0xa17e2c32,0xad002d72,0xabb71cb6,0xa17e2515,0x2dfea9f1,0xac072c87,0xafed2e99,0x1fd91648,0x2fd4afbc,0xa9f12b05,0xad962f91,0x26a1a44e,0x2aaaae3f,0xa76528d5,0x251528d5,0x2993a875,
0x2fe6aeb5,0x2ddcadba,0xafff2f6e,0x2ed0aeb5,0x2e3fafbc,0x2e1fadfe,0xad272f30,0x2f02aee9,0x1fd9ab5e,0x2e5eae3f,0x244e2875,0x2f30af1a,0xad962993,0x2e99ae7c,0x2e99ac32,0x2f5aaf46,
0x299329f1,0xa76525db,0x251525db,0x2aaa1648,0x28d52934,0xaf02acd8,0x230e244e,0x2fa02dfe,0x28142875,0xaf91aff8,0x1fd9217e,0x2ee92ff4,0x26a12765,0xaa4eaddc,0x16481cb6,0x26a12cb0,
0x2f022f46,0x2b5e2e7c,0x2b5e2c32,0x230ea993,0x2e5e2eb5,0xab051648,0x29342a4e,0x2ee92c5d,0x2d962dfe,0xafddae5e,0x25db2814,0x2f5a2ffc,0x2cb02d27,0xaddcafaf,0x1cb6230e,0x27652d27,
0x2fd42f91,0x2f6e2fed,0x2dba2e5e,0xa6a1ad4d,0x2fff2ff8,0x25152d00,0x2c322d00,0x2ddc28d5,0x2faf2fe6,0xae1fa993,0x28d52aaa,0x2faf2fc9,0x2ee92f5a,0xaf91afdd,0x1fd925db,0x28142d96,
0x2cd82b5e,0x2f912d00,0x2f302faf,0xac07af1a,0x2eb52ddc,0x2d962fc9,0x2d962e7c,0x2c871cb6,0x2fc92f5a,0xa99326a1,0x2aaa2c87,0x2fe62f5a,0x2ff42ffc,0xaff8ae5e,0x217e2814,0x28752dfe,
0x9fd9a875,0x2c07a17e,0x2fed2ff8,0xadfeaff4,0x29f12515,0x2fdd2f46,0x2eb52f80,0x29f1a765,0x2ddc2c87,0x25152d96,0x2c322d96,0x2fff2eb5,0x2fa02ee9,0xaf02ab05,0x230e2934,0x28d52e5e,
0xad96aee9,0xa5dbadfe,0x2fdd2f30,0xaf5aafbc,0xa765abb7,0x2f462b5e,0x2f802ff8,0x2515abb7,0x28d51cb6,0x2d002fc9,0x2d002e7c,0x2ff82ddc,0x2dfe2c5d,0xacd81648,0x244e2a4e,0x29342eb5,
0xaff8afc9,0xae3fafff,0x2f022d72,0xaff8ae7c,0xadfeaf5a,0x2c07a5db,0x2fed2fdd,0x9fd9ad96,0xa6a1ac07,0x2f6e2f91,0x2dba2f30,0x2fd42cd8,0x2aaa230e,0xa7652b5e,0x25152b5e,0x29932f02,
0xae7cac5d,0xafffad96,0x2d7229f1,0xafc9ac5d,0xaff4afbc,0xa17eadfe,0x2ff82f30,0xa875aee9,0xad4daf1a,0x2fed2d00,0x2e5e2faf,0x2f912b5e,0x1648a993,0x25db2e7c,0x25db2c32,0x29f12f46,
0xaddc9648,0xafe6a6a1,0xaed0a6a1,0x2fff2a4e,0xad27affc,0x2d00ac07,0xabb7afbc,0xae1f2934,0x2e5e230e,0x1fd92fa0,0x2f3028d5,0x244eaf02,0x2c872fe6,0xadbaaf46,0x2a4e2f80,0x2c872fc9,
0xa30e2d72,0xad272c32,0xad272515,0x2faf1cb6,0xafbcae99,0x1fd9af6e,0xad4db000,0xacd82c87,0x2a4eab05,0x2c5d2fbc,0x2eb5244e,0x1648af91,0x2ed02fa0,0xaf80ad00,0x2aaa2faf,0x2cb02fa0,
0x2c872ffc,0x16482fbc,0xa9f12c07,0x2e99a934,0xaf80a8d5,0xac32afaf,0xae7cafaf,0xaaaa2e1f,0xa30eaed0,0x2f1a2d72,0x2e1f9cb6,0xa30eafe6,0x2fed2dba,0xaffca6a1,0x2b052fd4,0x2cd82f6e,
0x2fbc2e1f,0x2d4d2f02,0x9fd92e3f,0x2cd8ad27,0xac872993,0xaf5aacb0,0xaf5aaed0,0xa6a12f46,0xacb0b000,0x2fff25db,0x2d72a6a1,0xa765b000,0x2faf2934,0xaf1a2814,0x2b5e2fed,0x2d002f30,
0x2f30230e,0x2fed28d5,0x28142fa0,0x2934af02,0x16482ed0,0xafd41cb6,0xafddad72,0x16482fe6,0xaf46aeb5,0x2ed0a9f1,0x2cb0a9f1,0xa993afdd,0x2e1fa44e,0xad002d4d,0x2bb72ffc,0x2d272ee9,
0x2a4eacd8,0x2eb5ab05,0x2c5d2ffc,0x1648afed,0x2cb02ff4,0xad722d27,0xafffab5e,0x27652ff4,0xaff8aaaa,0x2bb7ae7c,0x2bb7ac32,0xab5eaf80,0x2b05ac87,0xa8142f6e,0x2c073000,0x2d4d2e99,
0xa8d5afe6,0x2875af80,0x2e3f2f46,0xa8d5afc9,0x2f912dba,0xa44e2fd4,0xafbca6a1,0x2b052f6e,0xae99244e,0x9648affc,0x29f1ad4d,0xac87aee9,0x1cb6af02,0x25152ff8,0x2c322ff8,0x2d722e3f,
0xaed0ae99,0xaaaaaf5a,0x2f802d96,0xacb0ae99,0x2faf244e,0x2b5e2f30,0xaf1a1fd9,0x2d002e5e,0xab052d27,0xac07af02,0x2814ae3f,0xad4dae1f,0xa9f1afff,0x2c5d2ed0,0x2c5d2fe6,0x2d962ddc,
0xaf46aa4e,0xac32ac87,0xae7cac87,0x29932dba,0x2f1a2b05,0xa8752fed,0x2e3f2cd8,0x2b5eaffc,0xaee9abb7,0x2f30ae1f,0xadfead27,0xafbc2d00,0x2eb52c32,0xaf6e1cb6,0x2dba2d72,0x2eb52515,
0xafaf2993,0xafa02515,0xafa0a765,0x2d002aaa,0x2feda6a1,0x29342d96,0x2f3029f1,0x2814afd4,0xb0001fd9,0x2c87afed,0xae99ac07,0xaf6e2dfe,0x2fe6217e,0xafff2bb7,0x2ddc2d00,0x2ed0217e,
0xac5d2f30,0xaf5a2e5e,0xb000244e,0x2eb51fd9,0x2ddcae1f,0x2e7c230e,0x2fc9230e,0x1cb6af1a,0xaf022cb0,0x217eaf46,0xaf1aa993,0xaf022ed0,0x2fbca9f1,0xaf302e99,0x2dfe2c87,0x2ee91648,
0x244e2fa0,0xab052ff4,0xaf912bb7,0x2fbca8d5,0x26a1afff,0x3000ac32,0x3000a515,0xa5dbaddc,0xac322f6e,0xaaaaac5d,0xaf80a5db,0xae7c2f6e,0x2e3fadfe,0xad272fed,0x2e1f2c07,0x2f029fd9,
0x2dfe2bb7,0x28142d27,0xae5e2e1f,0x2ffcad00,0xaa4eae7c,0x2e99af80,0x2fd4aaaa,0xaa4eac32,0x9cb62fdd,0xae7c9648,0xafc99648,0xaddc2fd4,0x2b5eafbc,0xa8752f91,0x2e3f2b05,0x2f1aa44e,
0x3000a814,0x2e999fd9,0xac872f91,0x2f6eaee9,0xaed0a875,0x2993afa0,0x2f46ad27,0xacb0a875,0x2b5e2ddc,0xaff42c32,0xaff42515,0xad272fff,0x1fd9afd4,0x244e2d96,0x2e5e29f1,0x2f30a6a1,
0x2e1faed0,0x2ff4addc,0xa8752fff,0x2e1fafe6,0xaffc29f1,0xa814ac87,0x2e5eae99,0xadfe9648,0x2eb52814,0xaf5a2f30,0xb0002934,0xac5d2fed,0xa993ae3f,0x2c3228d5,0x2e7c28d5,0x2f46a875,
0x2515afd4,0x2d72b000,0x1cb62f5a,0x2c32afd4,0xae3f2ee9,0xae1f1fd9,0x2d27af91,0xaf022814,0x2ffca8d5,0xacd82ff4,0xafed2bb7,0xab052fa0,0xad96aaaa,0x2e99a515,0x2e992765,0x2f5aa993,
0x1cb6adba,0x2cb0aeb5,0x2765aeb5,0xaddc2f6e,0xaff82d4d,0xa30ea814,0xafaf2c07,0xa17e2b05,0xa44e2e3f,0xadfe2b5e,0xa9342f1a,0x2cd8a875,0x2fddacb0,0xb0002f80,0x2f6eaaaa,0x2fddaed0,
0xad009cb6,0xa17ea765,0xa17eacb0,0xabb72ddc,0xaee92fdd,0xad4d2a4e,0xaffc2dba,0x244e25db,0x29f12934,0xafd42ee9,0xa6a12e5e,0x2d96ab05,0x2fc9af1a,0xaf462ff4,0x2f80abb7,0x2fe6af1a,
0xafdd2d4d,0xadba2c07,0xaa4ea814,0xa5db2b05,0xaaaa2f1a,0xafc92f02,0xafe62f02,0x2993a17e,0x2e3fa765,0xafa02fff,0xa17e2d72,0x2e3facb0,0x2e5eb000,0xad4d2eb5,0x2f91ac5d,0x2fedaf5a,
0xaee92ff8,0xaffc2faf,0xad4d230e,0x244e217e,0x25db2aaa,0xaf6e2fe6,0xaf6e2fc9,0x2c5da993,0x2fe6adba,0xad722e99,0x1cb62c5d,0x2ed0adba,0x2bb7af30,0xa8d52c07,0x2fa0acd8,0x2ff4af91,
0xa9342e3f,0xae5e2f1a,0xaee92b5e,0x2b05a875,0x2dbaa765,0xac5d2d72,0xae992fff,0x2dbaacb0,0x2f80afd4,0xa7652a4e,0x25152a4e,0x2f46ae99,0x217eacd8,0x230e1fd9,0x2fafad4d,0x2ff8afbc,
0x29f1244e,0xa6a12934,0xafd42dfe,0x2d96acd8,0x2fe6ae3f,0x1cb6217e,0xad722fa0,0x2ed0ae3f,0x2d27af80,0x2875a515,0x28752765,0x2fa0af46,0xa934a5db,0x2c07aa4e,0x2fbcadba,0x2ffcafdd,
0x2f1aacb0,0x2bb7aaaa,0xaff42f80,0x2f1aaed0,0x2f30b000,0x2cd8ac5d,0xac072eb5,0x2f91af5a,0x25dbacd8,0x2dbaad4d,0x2a4e1fd9,0x2fddafbc,0xad722875,0x2e7cae1f,0x2fc9ae1f,0x2fffaff4,
0x2fc9afdd,0x2f80af6e,0xaf463000,0x2fe6afdd,0x2bb7ae5e,0x2fa0af91,0xa8d52d4d,0x2ff4afed,0xa934a17e,0x2fbcafaf,0x2c07a30e,0x2ffcaff8,0xaf5a2d72,0x2fd4afc9,0x2fd4ae7c,0x3000afff,
0x9d4d9e16,0xada6ae7d,0x9b769c84,0xabf0accf,0x985299e4,0xa897aa43,0x90b6957f,0xa102a5d8,0x13db0a48,0x242c1aad,0x191b1712,0x296d2783,0x1c201aad,0x2c632b1a,0x1db21ce9,0x2e112d3a,
0xa3f4a491,0xae51af42,0xa199a2c6,0xac70ad60,0x9e7ba06b,0xa922ab00,0x97129c20,0xa199a688,0x19e410b6,0x24aa1b76,0x1fa81d4d,0x2a112833,0x222f2102,0x2ce82bf0,0x2445235d,0x2ec92dd8,
0xa6a1a79c,0xaefcb004,0xa4aaa5a5,0xace8adf2,0xa166a35d,0xa9acabbe,0x99e49edf,0xa22fa738,0x1ce913db,0x25281c20,0x2262206b,0x2ab528a4,0x2528242c,0x2d6d2c63,0x271f2623,0x2f822e77,
0xa8a4a954,0xafa8b067,0xa688a7e8,0xad60ae84,0xa38fa528,0xaa37ac3d,0x9c20a0d0,0xa2c6a7e8,0x1edf157f,0x25a51c84,0x2478222f,0x2b592915,0x273825d8,0x2df22ccf,0x28fc284c,0x301d2f16,
0xa9f8aadb,0xb02ab0ca,0xa833a915,0xadd8af16,0xa4dca6a1,0xaac1ac9c,0x9d4da22f,0xa35da84c,0x206b1712,0x26231ce9,0x25bf23f4,0x2bfd2987,0x28a42783,0x2e772d3a,0x2a692987,0x307a2fb5,
0xab4cac31,0xb081b12e,0xa922aa37,0xae51afa8,0xa5f1a80d,0xab4cacfb,0x9e7ba38f,0xa3f4a8a4,0x21661852,0x26a11d4d,0x270524dc,0x2c5029f8,0x29ac2897,0x2efc2da6,0x2bd72ac1,0x30d7302a,
0xac50acf5,0xb0d7b192,0xaa11ab59,0xaec9b01d,0xa705a8ca,0xabd7ad5a,0x9fa8a478,0xa445a8fc,0x2262191b,0x271f1db2,0x282625bf,0x2ca22a69,0x2ab5296d,0x2f822e11,0x2ca22bfd,0x3135307a,
0xacfbadb9,0xb12eb1f7,0xab00ac3d,0xaf42b067,0xa80da987,0xac31adb9,0xa06ba528,0xa491a954,0x235d19e4,0x279c1e16,0x28ca26a1,0x2cf52adb,0x2bbe2a43,0x30042e7d,0x2d5a2c9c,0x319230ca,
0xb185b25c,0xb426b4cc,0xafbbb0b1,0xb1c6b306,0xac76ae18,0xaea3b08a,0xa4dca9ac,0xa738ac37,0x280d1e7b,0x2a0520d0,0x2d472b4c,0x2fdb2d6d,0x30472ee9,0x32663128,0x31f0311b,0x347933a8,
0xb1ddb2c1,0xb453b501,0xb01ab0fb,0xb204b352,0xacbcae77,0xaee9b0ba,0xa528aa05,0xa783ac63,0x284c1edf,0x2a432102,0x2d992bbe,0x30172da6,0x308a2f55,0x32aa315f,0x324f316b,0x34aa33fc,
0xb235b327,0xb481b537,0xb057b145,0xb242b39e,0xad01aed6,0xaf2fb0eb,0xa573aa5d,0xa7cfac90,0x288b1f44,0x2a822134,0x2deb2c18,0x30412ddf,0x30ce2fc2,0x32ef3196,0x32ae31bc,0x34db3428,
0xb28db38e,0xb4afb56d,0xb094b18f,0xb280b3eb,0xad47af36,0xaf75b11b,0xa5bfaab5,0xa80dacbc,0x28ca1fa8,0x2ac12166,0x2e3e2c50,0x306a2e18,0x31113017,0x333531cd,0x330d320e,0x350d3452,
0xb2e5b3f5,0xb4ddb5a3,0xb0d1b1da,0xb2beb41c,0xad8caf95,0xafbbb14b,0xa60aab0d,0xa833ace8,0x29092006,0x2b002199,0x2e902c89,0x30942e51,0x3155304d,0x337a3204,0x336d325f,0x3540347c,
0xb33eb42e,0xb50cb5da,0xb10eb224,0xb2fcb443,0xadd2aff5,0xb001b17c,0xa655ab65,0xa859ad14,0x29482039,0x2b4021cb,0x2ee32cc2,0x30be2e8a,0x31993084,0x33c0323b,0x33cd32b1,0x357234a6,
0xb398b463,0xb53ab612,0xb14bb26f,0xb33bb469,0xae18b02a,0xb024b1ac,0xa6a1abbe,0xa87ead40,0x2987206b,0x2b7f21fd,0x2f362cfb,0x30e72ec3,0x31dd30ba,0x34033273,0x34173303,0x35a534d1,
0xb3f2b497,0xb569b64a,0xb189b2bb,0xb37ab490,0xae5eb05a,0xb047b1dd,0xa6ecac0b,0xa8a4ad6d,0x29c6209d,0x2bbe222f,0x2f882d34,0x31112efc,0x322130f1,0x342632aa,0x34483356,0x35d934fc,
0xb599b682,0xb722b82e,0xb3b9b4b7,0xb4ddb5f9,0xb06ab20e,0xb185b398,0xa8caad99,0xa9f8aefc,0x2bfd2262,0x2cfb23f4,0x313b2f36,0x328d3081,0x344932e2,0x35693453,0x360d3527,0x37bd368b,
0xb5c9b6bb,0xb755b84d,0xb3f8b4df,0xb4feb622,0xb08db23e,0xb1a9b3ca,0xa8f0adc5,0xaa1eaf29,0x2c1e2294,0x2d1b2413,0x31652f6f,0x32b7309d,0x346d331a,0x358e3470,0x36413553,0x37f536ba,
0xb5f9b6f5,0xb789b86d,0xb41cb506,0xb51fb64c,0xb0b1b26f,0xb1cdb3fc,0xa915adf2,0xaa43af55,0x2c3d22c6,0x2d3a242c,0x318f2fa8,0x32e230ba,0x34903352,0x35b3348d,0x3676357e,0x381736e8,
0xb629b72f,0xb7bdb88d,0xb43cb52e,0xb540b676,0xb0d4b2a1,0xb1f0b417,0xa93bae1e,0xaa69af82,0x2c5d22f9,0x2d5a2445,0x31b92fe2,0x330d30d7,0x34b4338b,0x35d934aa,0x36ab35ab,0x38343717,
0xb65ab76a,0xb7f1b8ad,0xb45cb556,0xb561b6a0,0xb0f7b2d2,0xb214b430,0xa961ae4b,0xaa8fafaf,0x2c7d232b,0x2d79245f,0x31e3300e,0x333830f4,0x34d833c3,0x35fe34c7,0x36e035d7,0x38513746,
0xb68bb7a5,0xb813b8ce,0xb47cb57e,0xb582b6ca,0xb11bb303,0xb238b449,0xa987ae77,0xaab5afdb,0x2c9c235d,0x2d992478,0x320e302a,0x33633111,0x34fc33fc,0x362434e4,0x37173604,0x386f3775,
0xb6bdb7e2,0xb82eb8f0,0xb49cb5a7,0xb5a3b6f5,0xb13eb335,0xb25cb463,0xa9acaea3,0xaadbb004,0x2cbc238f,0x2db92491,0x32383047,0x338e312e,0x3520341a,0x364a3501,0x374d3631,0x388d37a5,
0xb6efb80f,0xb849b911,0xb4bdb5d0,0xb5c5b720,0xb162b366,0xb280b47c,0xa9d2aed0,0xab00b01a,0x2cdb23c2,0x2dd824aa,0x32623064,0x33b9314b,0x35453437,0x3670351f,0x3785365e,0x38ab37d6,
0xb865b934,0xb94dba5c,0xb5e7b74c,0xb6fcb85a,0xb2a4b495,0xb3c6b564,0xab26b031,0xac2bb0e4,0x2df824c3,0x2ef6258c,0x33e43168,0x34a13252,0x3697353c,0x37d4362d,0x38ca3803,0x39d038d0,
0xb880b957,0xb96bba84,0xb609b777,0xb720b872,0xb2c8b4af,0xb3ebb57e,0xab4cb047,0xac3db0fb,0x2e1824dc,0x2f1625a5,0x34083185,0x34b7326f,0x36bd355a,0x37fd364c,0x38e9381c,0x39f338eb,
0xb89cb97a,0xb98abaad,0xb62bb7a4,0xb744b88a,0xb2ecb4c9,0xb408b599,0xab72b05d,0xac50b111,0x2e3724f5,0x2f3625bf,0x341e31a2,0x34ce328d,0x36e43577,0x3813366b,0x39093835,0x3a173906,
0xb8b9b99e,0xb9aabad7,0xb64db7d0,0xb768b8a2,0xb310b4e2,0xb41ab5b3,0xab98b074,0xac63b128,0x2e57250f,0x2f5525d8,0x343331c0,0x34e432aa,0x370b3595,0x3828368a,0x3929384e,0x3a3b3922,
0xb8d6b9c3,0xb9cabb02,0xb670b7fd,0xb78cb8ba,0xb335b4fc,0xb42db5ce,0xabbeb08a,0xac76b13e,0x2e772528,0x2f7525f1,0x344931dd,0x34fa32c8,0x373335b3,0x383d36a9,0x39493868,0x3a60393e,
0xb8f3b9e8,0xb9ebbb2d,0xb693b815,0xb7b1b8d2,0xb359b516,0xb43fb5e9,0xabe3b0a1,0xac89b155,0x2e972541,0x2f95260a,0x345f31fa,0x351132e5,0x375b35d2,0x385236c8,0x396a3881,0x3a86395a,
0xb910ba0e,0xba0cbb59,0xb6b6b82c,0xb7d6b8eb,0xb37db530,0xb452b604,0xac05b0b7,0xac9cb16b,0x2eb6255a,0x2fb52623,0x34753217,0x35273303,0x378335f0,0x386836e8,0x398c389b,0x3aac3977,
0xb92eba35,0xba2dbb87,0xb6d9b843,0xb7fbb904,0xb3a2b54a,0xb464b61e,0xac18b0ce,0xacafb182,0x2ed62573,0x2fd5263c,0x348b3235,0x353e3321,0x37ab360e,0x387d3708,0x39ae38b6,0x3ad33994,
0x9ce99db2,0xad3aae11,0x9aad9c20,0xab1aac63,0x9712991b,0xa783a96d,0x8a4893db,0x9aada42c,0x157f10b6,0x25d82102,0x19e41852,0x2a432897,0x1c841b76,0x2ccf2bf0,0x1e161d4d,0x2e7d2da6,
0xa35da445,0xadd8aec9,0xa102a22f,0xabf0ace8,0x9d4d9fa8,0xa833aa11,0x90b699e4,0x9b76a4aa,0x1c201712,0x26882199,0x206b1e7b,0x2b002922,0x22c62199,0x2d602c70,0x249123f4,0x2f422e51,
0xa623a71f,0xae77af82,0xa42ca528,0xac63ad6d,0xa06ba262,0xa8a4aab5,0x93db9ce9,0x9c20a528,0x1edf19e4,0x2738222f,0x235d2166,0x2bbe29ac,0x25a524aa,0x2df22ce8,0x279c26a1,0x30042efc,
0xa84ca8fc,0xaf16b01d,0xa5d8a738,0xaccfadf2,0xa22fa478,0xa915ab59,0x957f9edf,0x9c84a5a5,0x20d01c20,0x27e822c6,0x2528238f,0x2c3d2a37,0x27e82688,0x2e842d60,0x295428a4,0x30672fa8,
0xa987aa69,0xafb5b07a,0xa783a8a4,0xad3aae77,0xa3f4a5bf,0xa987abfd,0x9712a06b,0x9ce9a623,0x222f1d4d,0x284c235d,0x26a124dc,0x2c9c2ac1,0x29152833,0x2f162dd8,0x2adb29f8,0x30ca302a,
0xaac1abd7,0xb02ab0d7,0xa897a9ac,0xada6aefc,0xa4dca705,0xa9f8ac50,0x9852a166,0x9d4da6a1,0x238f1e7b,0x28a423f4,0x280d25f1,0x2cfb2b4c,0x2a372922,0x2fa82e51,0x2c312b4c,0x312e3081,
0xabfdaca2,0xb07ab135,0xa96daab5,0xae11af82,0xa5bfa826,0xaa69aca2,0x991ba262,0x9db2a71f,0x24781fa8,0x28fc2445,0x28ca2705,0x2d5a2bd7,0x2b592a11,0x301d2ec9,0x2cf52c50,0x319230d7,
0xac9cad5a,0xb0cab192,0xaa43abbe,0xae7db004,0xa6a1a8ca,0xaadbacf5,0x99e4a35d,0x9e16a79c,0x2528206b,0x29542491,0x2987280d,0x2db92c31,0x2c3d2b00,0x30672f42,0x2db92cfb,0x31f7312e,
0xb11bb1f0,0xb3a8b479,0xaee9b047,0xb128b266,0xab4cad47,0xad6dafdb,0x9e7ba80d,0xa0d0aa05,0x29ac24dc,0x2c372738,0x2e182c76,0x308a2ea3,0x30b12fbb,0x330631c6,0x325c3185,0x34cc3426,
0xb16bb24f,0xb3fcb4aa,0xaf55b08a,0xb15fb2aa,0xabbead99,0xada6b017,0x9edfa84c,0xa102aa43,0x2a052528,0x2c632783,0x2e772cbc,0x30ba2ee9,0x30fb301a,0x33523204,0x32c131dd,0x35013453,
0xb1bcb2ae,0xb428b4db,0xafc2b0ce,0xb196b2ef,0xac18adeb,0xaddfb041,0x9f44a88b,0xa134aa82,0x2a5d2573,0x2c9027cf,0x2ed62d01,0x30eb2f2f,0x31453057,0x339e3242,0x33273235,0x35373481,
0xb20eb30d,0xb452b50d,0xb017b111,0xb1cdb335,0xac50ae3e,0xae18b06a,0x9fa8a8ca,0xa166aac1,0x2ab525bf,0x2cbc280d,0x2f362d47,0x311b2f75,0x318f3094,0x33eb3280,0x338e328d,0x356d34af,
0xb25fb36d,0xb47cb540,0xb04db155,0xb204b37a,0xac89ae90,0xae51b094,0xa006a909,0xa199ab00,0x2b0d260a,0x2ce82833,0x2f952d8c,0x314b2fbb,0x31da30d1,0x341c32be,0x33f532e5,0x35a334dd,
0xb2b1b3cd,0xb4a6b572,0xb084b199,0xb23bb3c0,0xacc2aee3,0xae8ab0be,0xa039a948,0xa1cbab40,0x2b652655,0x2d142859,0x2ff52dd2,0x317c3001,0x3224310e,0x344332fc,0x342e333e,0x35da350c,
0xb303b417,0xb4d1b5a5,0xb0bab1dd,0xb273b403,0xacfbaf36,0xaec3b0e7,0xa06ba987,0xa1fdab7f,0x2bbe26a1,0x2d40287e,0x302a2e18,0x31ac3024,0x326f314b,0x3469333b,0x34633398,0x3612353a,
0xb356b448,0xb4fcb5d9,0xb0f1b221,0xb2aab426,0xad34af88,0xaefcb111,0xa09da9c6,0xa22fabbe,0x2c0b26ec,0x2d6d28a4,0x305a2e5e,0x31dd3047,0x32bb3189,0x3490337a,0x349733f2,0x364a3569,
0xb527b60d,0xb68bb7bd,0xb2e2b449,0xb453b569,0xaf36b13b,0xb081b28d,0xa262abfd,0xa3f4acfb,0x2d9928ca,0x2efc29f8,0x320e306a,0x33983185,0x34b733b9,0x35f934dd,0x36823599,0x382e3722,
0xb553b641,0xb6bab7f5,0xb31ab46d,0xb470b58e,0xaf6fb165,0xb09db2b7,0xa294ac1e,0xa413ad1b,0x2dc528f0,0x2f292a1e,0x323e308d,0x33ca31a9,0x34df33f8,0x362234fe,0x36bb35c9,0x384d3755,
0xb57eb676,0xb6e8b817,0xb352b490,0xb48db5b3,0xafa8b18f,0xb0bab2e2,0xa2c6ac3d,0xa42cad3a,0x2df22915,0x2f552a43,0x326f30b1,0x33fc31cd,0x3506341c,0x364c351f,0x36f535f9,0x386d3789,
0xb5abb6ab,0xb717b834,0xb38bb4b4,0xb4aab5d9,0xafe2b1b9,0xb0d7b30d,0xa2f9ac5d,0xa445ad5a,0x2e1e293b,0x2f822a69,0x32a130d4,0x341731f0,0x352e343c,0x36763540,0x372f3629,0x388d37bd,
0xb5d7b6e0,0xb746b851,0xb3c3b4d8,0xb4c7b5fe,0xb00eb1e3,0xb0f4b338,0xa32bac7d,0xa45fad79,0x2e4b2961,0x2faf2a8f,0x32d230f7,0x34303214,0x3556345c,0x36a03561,0x376a365a,0x38ad37f1,
0xb604b717,0xb775b86f,0xb3fcb4fc,0xb4e4b624,0xb02ab20e,0xb111b363,0xa35dac9c,0xa478ad99,0x2e772987,0x2fdb2ab5,0x3303311b,0x34493238,0x357e347c,0x36ca3582,0x37a5368b,0x38ce3813,
0xb631b74d,0xb7a5b88d,0xb41ab520,0xb501b64a,0xb047b238,0xb12eb38e,0xa38facbc,0xa491adb9,0x2ea329ac,0x30042adb,0x3335313e,0x3463325c,0x35a7349c,0x36f535a3,0x37e236bd,0x38f0382e,
0xb65eb785,0xb7d6b8ab,0xb437b545,0xb51fb670,0xb064b262,0xb14bb3b9,0xa3c2acdb,0xa4aaadd8,0x2ed029d2,0x301a2b00,0x33663162,0x347c3280,0x35d034bd,0x372035c5,0x380f36ef,0x39113849,
0xb803b8ca,0xb8d0b9d0,0xb53cb697,0xb62db7d4,0xb168b3e4,0xb252b4a1,0xa4c3adf8,0xa58caef6,0x30312b26,0x30e42c2b,0x349532a4,0x356433c6,0x374c35e7,0x385a36fc,0x39343865,0x3a5c394d,
0xb81cb8e9,0xb8ebb9f3,0xb55ab6bd,0xb64cb7fd,0xb185b408,0xb26fb4b7,0xa4dcae18,0xa5a5af16,0x30472b4c,0x30fb2c3d,0x34af32c8,0x357e33eb,0x37773609,0x38723720,0x39573880,0x3a84396b,
0xb835b909,0xb906ba17,0xb577b6e4,0xb66bb813,0xb1a2b41e,0xb28db4ce,0xa4f5ae37,0xa5bfaf36,0x305d2b72,0x31112c50,0x34c932ec,0x35993408,0x37a4362b,0x388a3744,0x397a389c,0x3aad398a,
0xb84eb929,0xb922ba3b,0xb595b70b,0xb68ab828,0xb1c0b433,0xb2aab4e4,0xa50fae57,0xa5d8af55,0x30742b98,0x31282c63,0x34e23310,0x35b3341a,0x37d0364d,0x38a23768,0x399e38b9,0x3ad739aa,
0xb868b949,0xb93eba60,0xb5b3b733,0xb6a9b83d,0xb1ddb449,0xb2c8b4fa,0xa528ae77,0xa5f1af75,0x308a2bbe,0x313e2c76,0x34fc3335,0x35ce342d,0x37fd3670,0x38ba378c,0x39c338d6,0x3b0239ca,
0xb881b96a,0xb95aba86,0xb5d2b75b,0xb6c8b852,0xb1fab45f,0xb2e5b511,0xa541ae97,0xa60aaf95,0x30a12be3,0x31552c89,0x35163359,0x35e9343f,0x38153693,0x38d237b1,0x39e838f3,0x3b2d39eb,
0xb89bb98c,0xb977baac,0xb5f0b783,0xb6e8b868,0xb217b475,0xb303b527,0xa55aaeb6,0xa623afb5,0x30b72c05,0x316b2c9c,0x3530337d,0x36043452,0x382c36b6,0x38eb37d6,0x3a0e3910,0x3b593a0c,
0xb8b6b9ae,0xb994bad3,0xb60eb7ab,0xb708b87d,0xb235b48b,0xb321b53e,0xa573aed6,0xa63cafd5,0x30ce2c18,0x31822caf,0x354a33a2,0x361e3464,0x384336d9,0x390437fb,0x3a35392e,0x3b873a2d,
0x214d2216,0x319b326c,0x1f762084,0x2fe830c8,0x1c521de4,0x2c962e40,0x14b6197f,0x250229d7,0x97db8e48,0xa82c9ead,0x9d1b9b12,0xad6bab82,0xa0209ead,0xb05eaf14,0xa1b2a0e9,0xb204b131,
0x27f32890,0x3241332b,0x259826c6,0x306a3156,0x227b246b,0x2d202efb,0x1b122020,0x25982a87,0x9de494b6,0xa8aa9f76,0xa3a8a14d,0xae0eac32,0xa62fa502,0xb0e1afe8,0xa845a75d,0xb2b6b1cc,
0x2aa02b9b,0x32e733e8,0x28aa29a5,0x30e131e5,0x2566275d,0x2daa2fb6,0x1de422df,0x262f2b36,0xa0e997db,0xa927a020,0xa661a46b,0xaeb0aca2,0xa927a82c,0xb163b05e,0xab1daa22,0xb368b266,
0x2ca22d52,0x338d3452,0x2a872be6,0x31563273,0x278f2927,0x2e333039,0x202024cf,0x26c62be6,0xa2df997f,0xa9a5a084,0xa877a62f,0xaf53ad13,0xab36a9d7,0xb1e5b0c8,0xacfaac4b,0xb40cb300,
0x2df52ed6,0x341834b0,0x2c322d13,0x31cc3300,0x28dc2aa0,0x2ebd3096,0x214d262f,0x275d2c4b,0xa46b9b12,0xaa22a0e9,0xa9bea7f3,0xaff5ad84,0xaca2ab82,0xb266b131,0xae65ad84,0xb464b399,
0x2f46302c,0x346a350c,0x2d202e33,0x3241338d,0x29f02c0c,0x2f4630f3,0x227b278f,0x27f32ca2,0xa5669c52,0xaaa0a14d,0xab04a8dc,0xb04badf5,0xadaaac96,0xb2e7b19b,0xafcfaebd,0xb4bcb418,
0x304b30ed,0x34bc3568,0x2e0e2f53,0x32b6340c,0x2b042cc8,0x2fcf3150,0x23a82877,0x28452cfa,0xa6619d1b,0xab1da1b2,0xac25a9be,0xb09cae65,0xaeb0ad6b,0xb368b204,0xb09caff5,0xb512b464,
0x30f331ad,0x350c35c4,0x2efb3039,0x332b3452,0x2c0c2d84,0x302c31ad,0x246b2927,0x28902d52,0xa75d9de4,0xab9ba216,0xacc8aaa0,0xb0edaed6,0xafb6ae40,0xb3e8b26c,0xb150b096,0xb568b4b0,
0x355d361e,0x37c63867,0x339f3497,0x359836b4,0x3071320a,0x32913473,0x28dc2daa,0x2b363032,0xac0ca27b,0xae01a4cf,0xb13eaf46,0xb3bdb163,0xb434b2d5,0xb627b506,0xb5beb4fa,0xb826b73e,
0x35ac3678,0x3808388f,0x340934dd,0x35cf36f5,0x30b53266,0x32d534a0,0x29272e01,0x2b82305e,0xac4ba2df,0xae40a502,0xb18eafb6,0xb406b19b,0xb473b33d,0xb663b539,0xb612b545,0xb84cb784,
0x35fb36d0,0x382c38b7,0x34433521,0x36073736,0x30f932c2,0x331834ce,0x29722e59,0x2bcd308a,0xac89a344,0xae7ea534,0xb1dfb013,0xb42eb1d2,0xb4b3b3a5,0xb6a0b56b,0xb666b58f,0xb872b7c9,
0x36493728,0x385038de,0x347c3565,0x363e3776,0x313e331e,0x335c34fa,0x29be2eb0,0x2c0c30b5,0xacc8a3a8,0xaebda566,0xb22fb04b,0xb455b20a,0xb4f1b406,0xb6dcb59d,0xb6b9b5d8,0xb898b807,
0x3697377e,0x38743904,0x34b635a9,0x367537b6,0x3182337a,0x339f3527,0x2a092f08,0x2c3230e1,0xad07a406,0xaefba598,0xb27fb083,0xb47cb241,0xb530b43a,0xb717b5cf,0xb70cb621,0xb8bdb828,
0x36e437d4,0x3897392a,0x34ee35ed,0x36ab37f5,0x31c633d6,0x33e23554,0x2a542f5f,0x2c57310c,0xad45a439,0xaf3aa5cb,0xb2cfb0bb,0xb4a4b279,0xb56eb46d,0xb752b601,0xb75db669,0xb8e1b84a,
0x37303814,0x38b9394e,0x3527362f,0x36e1381a,0x320a3418,0x34123580,0x2aa02fb6,0x2c7d3137,0xad84a46b,0xaf78a5fd,0xb31eb0f3,0xb4cbb2b0,0xb5acb4a0,0xb78cb632,0xb7adb6b1,0xb905b86b,
0x377c383e,0x38db3972,0x355f3672,0x37173838,0x324e3446,0x343435ac,0x2aeb3007,0x2ca23163,0xadc3a49d,0xafb6a62f,0xb36eb12b,0xb4f1b2e7,0xb5eab4d4,0xb7c6b663,0xb7fdb6f8,0xb928b88b,
0x38fd3996,0x39f33a91,0x374c3857,0x3874393e,0x345535d8,0x355d3730,0x2cc8318e,0x2df532e7,0xaff5a661,0xb0f3a7f3,0xb518b31e,0xb649b46a,0xb800b694,0xb8dbb808,0xb94bb8ab,0xba45b99b,
0x391e39b8,0x3a0f3aad,0x37813875,0x388c3959,0x34763604,0x357d375a,0x2cee31b9,0x2e1a3312,0xb01aa694,0xb112a813,0xb53fb356,0xb66fb485,0xb81cb6c5,0xb8f5b81f,0xb96db8cb,0xba61b9b7,
0x393e39da,0x3a2b3ac7,0x37b63893,0x38a53974,0x3497362f,0x359d3784,0x2d1331e5,0x2e40333d,0xb039a6c6,0xb131a82c,0xb565b38d,0xb694b4a0,0xb838b6f5,0xb90fb836,0xb98eb8ea,0xba7cb9d2,
0x395e39fb,0x3a453ae0,0x37ea38b0,0x38bd398e,0x34b9365b,0x35be37ad,0x2d393210,0x2e653368,0xb058a6f8,0xb150a845,0xb58cb3c3,0xb6b9b4bc,0xb854b725,0xb928b84c,0xb9aeb909,0xba97b9ed,
0x397d3a1b,0x3a5f3af9,0x380f38cd,0x38d539a8,0x34da3686,0x35de37d7,0x2d5e323b,0x2e8b3393,0xb077a72a,0xb16fa85e,0xb5b2b3fa,0xb6deb4d7,0xb870b755,0xb941b863,0xb9ceb927,0xbab0ba07,
0x399b3a3a,0x3a793b10,0x382838ea,0x38ed39c1,0x34fa36b1,0x35fe3800,0x2d843266,0x2eb033bd,0xb096a75d,0xb18ea877,0xb5d8b418,0xb703b4f1,0xb88bb784,0xb95ab879,0xb9edb945,0xbac9ba21,
0x39b93a58,0x3a913b26,0x38423906,0x390439da,0x351b36dc,0x361e3814,0x2daa3291,0x2ed633e8,0xb0b5a78f,0xb1ada890,0xb5feb434,0xb728b50c,0xb8a6b7b3,0xb972b88f,0xba0bb962,0xbae0ba3a,
0x39d73a75,0x3aa93b3c,0x385b3922,0x391b39f2,0x353c3706,0x363e3828,0x2dcf32bc,0x2efb3409,0xb0d4a7c1,0xb1cca8aa,0xb624b44f,0xb74cb527,0xb8c1b7e2,0xb98ab8a5,0xba29b97f,0xbaf7ba52,
0x3ac03b50,0x3b5e3bcb,0x39323a0a,0x39de3ab8,0x365e383c,0x375738d7,0x2f21341f,0x302634c8,0xb1eba8c3,0xb2e1a98c,0xb770b542,0xb846b615,0xb9a2b8bb,0xba51b960,0xbb0dba6a,0xbb9cbb11,
0x3ad73b63,0x3b6e3bd6,0x39493a22,0x39f23acb,0x367d3850,0x377638ea,0x2f463434,0x303934dd,0xb20aa8dc,0xb300a9a5,0xb795b55d,0xb857b62f,0xb9b9b8d0,0xba65b974,0xbb22ba81,0xbba9bb24,
0x3aec3b75,0x3b7d3bdf,0x395f3a39,0x3a063ade,0x369d3864,0x379538fd,0x2f6c3449,0x304b34f1,0xb229a8f5,0xb31ea9be,0xb7b8b577,0xb868b649,0xb9d0b8e5,0xba79b987,0xbb36ba97,0xbbb6bb35,
0x3b013b86,0x3b8c3be7,0x39753a4f,0x3a193af0,0x36bc3878,0x37b3390f,0x2f91345e,0x305e3506,0xb247a90e,0xb33da9d7,0xb7dcb592,0xb879b663,0xb9e7b8fa,0xba8cb99a,0xbb4abaad,0xbbc2bb46,
0x3b153b96,0x3b993bee,0x398a3a65,0x3a2d3b02,0x36dc388b,0x37d13921,0x2fb63473,0x3071351b,0xb266a927,0xb35ca9f0,0xb800b5ac,0xb88ab67d,0xb9fdb90f,0xba9fb9ad,0xbb5cbac3,0xbbccbb56,
0x3b283ba5,0x3ba63bf4,0x39a03a7a,0x3a3f3b13,0x36fb389e,0x37ef3933,0x2fdc3488,0x30833530,0xb285a940,0xb37aaa09,0xb811b5c7,0xb89bb697,0xba12b924,0xbab1b9c0,0xbb6dbad7,0xbbd6bb65,
0x3b3b3bb3,0x3bb23bf9,0x39b53a8f,0x3a523b24,0x371a38b2,0x38073945,0x3001349d,0x30963545,0xb2a4a959,0xb399aa22,0xb823b5e1,0xb8abb6b1,0xba28b938,0xbac3b9d2,0xbb7ebaeb,0xbbdfbb74,
0x3b4d3bc0,0x3bbd3bfc,0x39ca3aa4,0x3a643b34,0x373938c5,0x38153957,0x301334b3,0x30a9355a,0xb2c2a972,0xb3b7aa3b,0xb834b5fb,0xb8bcb6ca,0xba3cb94c,0xbad4b9e4,0xbb8dbaff,0xbbe6bb82,
0x20e921b2,0x31313204,0x1ead2020,0x2f14305e,0x1b121d1b,0x2b822d6b,0xe4817db,0x1ead282c,0x997f94b6,0xa9d7a502,0x9de49c52,0xae40ac96,0xa0849f76,0xb0c8afe8,0xa216a14d,0xb26cb19b,
0x275d2845,0x31cc32b6,0x2502262f,0x2fe830e1,0x214d23a8,0x2c322e0e,0x14b61de4,0x1f7628aa,0xa0209b12,0xaa87a598,0xa46ba27b,0xaefbad20,0xa6c6a598,0xb156b06a,0xa890a7f3,0xb32bb241,
0x2a222b1d,0x32663368,0x282c2927,0x305e3163,0x246b2661,0x2ca22eb0,0x17db20e9,0x20202927,0xa2df9de4,0xab36a62f,0xa75da566,0xafb6adaa,0xa9a5a8aa,0xb1e5b0e1,0xab9baaa0,0xb3e8b2e7,
0x2c4b2cfa,0x3300340c,0x29d72b36,0x30c831e5,0x262f2877,0x2d132f53,0x197f22df,0x208429a5,0xa4cfa020,0xabe6a6c6,0xa927a78f,0xb039ae33,0xabe6aa87,0xb273b156,0xad52aca2,0xb452b38d,
0x2d842e65,0x33993464,0x2b822ca2,0x31313266,0x27f329be,0x2d842ff5,0x1b12246b,0x20e92a22,0xa62fa14d,0xac4ba75d,0xaaa0a8dc,0xb096aebd,0xad13ac32,0xb300b1cc,0xaed6adf5,0xb4b0b418,
0x2ebd2fcf,0x341834bc,0x2c962daa,0x319b32e7,0x28dc2b04,0x2df5304b,0x1c522566,0x214d2aa0,0xa78fa27b,0xaca2a7f3,0xac0ca9f0,0xb0f3af46,0xae33ad20,0xb38db241,0xb02caf46,0xb50cb46a,
0x2ff5309c,0x34643512,0x2d6b2eb0,0x32043368,0x29be2c25,0x2e65309c,0x1d1b2661,0x21b22b1d,0xa877a3a8,0xacfaa845,0xacc8ab04,0xb150afcf,0xaf53ae0e,0xb40cb2b6,0xb0edb04b,0xb568b4bc,
0x30963150,0x34b03568,0x2e402fb6,0x326c33e8,0x2aa02cc8,0x2ed630ed,0x1de4275d,0x22162b9b,0xa927a46b,0xad52a890,0xad84ac0c,0xb1adb02c,0xb039aefb,0xb452b32b,0xb1adb0f3,0xb5c4b50c,
0x34fa35be,0x373e3826,0x32d53434,0x35063627,0x2f46313e,0x316333bd,0x227b2c0c,0x24cf2e01,0xadaaa8dc,0xb032ab36,0xb20ab071,0xb473b291,0xb497b39f,0xb6b4b598,0xb61eb55d,0xb867b7c6,
0x35453612,0x3784384c,0x333d3473,0x35393663,0x2fb6318e,0x319b3406,0x22df2c4b,0x25022e40,0xae01a927,0xb05eab82,0xb266b0b5,0xb4a0b2d5,0xb4ddb409,0xb6f5b5cf,0xb678b5ac,0xb88fb808,
0x358f3666,0x37c93872,0x33a534b3,0x356b36a0,0x301331df,0x31d2342e,0x23442c89,0x25342e7e,0xae59a972,0xb08aabcd,0xb2c2b0f9,0xb4ceb318,0xb521b443,0xb736b607,0xb6d0b5fb,0xb8b7b82c,
0x35d836b9,0x38073898,0x340634f1,0x359d36dc,0x304b322f,0x320a3455,0x23a82cc8,0x25662ebd,0xaeb0a9be,0xb0b5ac0c,0xb31eb13e,0xb4fab35c,0xb565b47c,0xb776b63e,0xb728b649,0xb8deb850,
0x3621370c,0x382838bd,0x343a3530,0x35cf3717,0x3083327f,0x3241347c,0x24062d07,0x25982efb,0xaf08aa09,0xb0e1ac32,0xb37ab182,0xb527b39f,0xb5a9b4b6,0xb7b6b675,0xb77eb697,0xb904b874,
0x3669375d,0x384a38e1,0x346d356e,0x36013752,0x30bb32cf,0x327934a4,0x24392d45,0x25cb2f3a,0xaf5faa54,0xb10cac57,0xb3d6b1c6,0xb554b3e2,0xb5edb4ee,0xb7f5b6ab,0xb7d4b6e4,0xb92ab897,
0x36b137ad,0x386b3905,0x34a035ac,0x3632378c,0x30f3331e,0x32b034cb,0x246b2d84,0x25fd2f78,0xafb6aaa0,0xb137ac7d,0xb418b20a,0xb580b412,0xb62fb527,0xb81ab6e1,0xb814b730,0xb94eb8b9,
0x36f837fd,0x388b3928,0x34d435ea,0x366337c6,0x312b336e,0x32e734f1,0x249d2dc3,0x262f2fb6,0xb007aaeb,0xb163aca2,0xb446b24e,0xb5acb434,0xb672b55f,0xb838b717,0xb83eb77c,0xb972b8db,
0x38ab394b,0x399b3a45,0x36943800,0x380838db,0x331e3518,0x346a3649,0x26612ff5,0x27f330f3,0xb18eacc8,0xb2e7adf5,0xb5d8b455,0xb730b55d,0xb857b74c,0xb93eb874,0xb996b8fd,0xba91b9f3,
0x38cb396d,0x39b73a61,0x36c5381c,0x381f38f5,0x3356353f,0x3485366f,0x2694301a,0x28133112,0xb1b9acee,0xb312ae1a,0xb604b476,0xb75ab57d,0xb875b781,0xb959b88c,0xb9b8b91e,0xbaadba0f,
0x38ea398e,0x39d23a7c,0x36f53838,0x3836390f,0x338d3565,0x34a03694,0x26c63039,0x282c3131,0xb1e5ad13,0xb33dae40,0xb62fb497,0xb784b59d,0xb893b7b6,0xb974b8a5,0xb9dab93e,0xbac7ba2b,
0x390939ae,0x39ed3a97,0x37253854,0x384c3928,0x33c3358c,0x34bc36b9,0x26f83058,0x28453150,0xb210ad39,0xb368ae65,0xb65bb4b9,0xb7adb5be,0xb8b0b7ea,0xb98eb8bd,0xb9fbb95e,0xbae0ba45,
0x392739ce,0x3a073ab0,0x37553870,0x38633941,0x33fa35b2,0x34d736de,0x272a3077,0x285e316f,0xb23bad5e,0xb393ae8b,0xb686b4da,0xb7d7b5de,0xb8cdb80f,0xb9a8b8d5,0xba1bb97d,0xbaf9ba5f,
0x394539ed,0x3a213ac9,0x3784388b,0x3879395a,0x341835d8,0x34f13703,0x275d3096,0x2877318e,0xb266ad84,0xb3bdaeb0,0xb6b1b4fa,0xb800b5fe,0xb8eab828,0xb9c1b8ed,0xba3ab99b,0xbb10ba79,
0x39623a0b,0x3a3a3ae0,0x37b338a6,0x388f3972,0x343435fe,0x350c3728,0x278f30b5,0x289031ad,0xb291adaa,0xb3e8aed6,0xb6dcb51b,0xb814b61e,0xb906b842,0xb9dab904,0xba58b9b9,0xbb26ba91,
0x397f3a29,0x3a523af7,0x37e238c1,0x38a5398a,0x344f3624,0x3527374c,0x27c130d4,0x28aa31cc,0xb2bcadcf,0xb409aefb,0xb706b53c,0xb828b63e,0xb922b85b,0xb9f2b91b,0xba75b9d7,0xbb3cbaa9,
0x3a6a3b0d,0x3b113b9c,0x38bb39a2,0x39603a51,0x35423770,0x36153846,0x28c331eb,0x298c32e1,0xb41faf21,0xb4c8b026,0xb83cb65e,0xb8d7b757,0xba0ab932,0xbab8b9de,0xbb50bac0,0xbbcbbb5e,
0x3a813b22,0x3b243ba9,0x38d039b9,0x39743a65,0x355d3795,0x362f3857,0x28dc320a,0x29a53300,0xb434af46,0xb4ddb039,0xb850b67d,0xb8eab776,0xba22b949,0xbacbb9f2,0xbb63bad7,0xbbd6bb6e,
0x3a973b36,0x3b353bb6,0x38e539d0,0x39873a79,0x357737b8,0x36493868,0x28f53229,0x29be331e,0xb449af6c,0xb4f1b04b,0xb864b69d,0xb8fdb795,0xba39b95f,0xbadeba06,0xbb75baec,0xbbdfbb7d,
0x3aad3b4a,0x3b463bc2,0x38fa39e7,0x399a3a8c,0x359237dc,0x36633879,0x290e3247,0x29d7333d,0xb45eaf91,0xb506b05e,0xb878b6bc,0xb90fb7b3,0xba4fb975,0xbaf0ba19,0xbb86bb01,0xbbe7bb8c,
0x3ac33b5c,0x3b563bcc,0x390f39fd,0x39ad3a9f,0x35ac3800,0x367d388a,0x29273266,0x29f0335c,0xb473afb6,0xb51bb071,0xb88bb6dc,0xb921b7d1,0xba65b98a,0xbb02ba2d,0xbb96bb15,0xbbeebb99,
0x3ad73b6d,0x3b653bd6,0x39243a12,0x39c03ab1,0x35c73811,0x3697389b,0x29403285,0x2a09337a,0xb488afdc,0xb530b083,0xb89eb6fb,0xb933b7ef,0xba7ab9a0,0xbb13ba3f,0xbba5bb28,0xbbf4bba6,
0x3aeb3b7e,0x3b743bdf,0x39383a28,0x39d23ac3,0x35e13823,0x36b138ab,0x295932a4,0x2a223399,0xb49db001,0xb545b096,0xb8b2b71a,0xb945b807,0xba8fb9b5,0xbb24ba52,0xbbb3bb3b,0xbbf9bbb2,
0x3aff3b8d,0x3b823be6,0x394c3a3c,0x39e43ad4,0x35fb3834,0x36ca38bc,0x297232c2,0x2a3b33b7,0xb4b3b013,0xb55ab0a9,0xb8c5b739,0xb957b815,0xbaa4b9ca,0xbb34ba64,0xbbc0bb4d,0xbbfcbbbd,
0x39b839ba,0x3a973ab5,0x39b339b5,0x3a583a78,0x39af39b1,0x3a153a37,0x39aa39ad,0x39cd39f2,0x39a639a8,0x398239a8,0x39a139a4,0x3933395b,0x399d399f,0x38e03909,0x3999399b,0x388938b5,
0xb979b972,0xb865b832,0xb986b980,0xb8c7b896,0xb994b98d,0xb924b8f6,0xb9a1b99b,0xb97db951,0xb9afb9a8,0xb9d2b9a8,0xb9bcb9b5,0xba21b9fa,0xb9c9b9c3,0xba6bba47,0xb9d6b9d0,0xbab0ba8e,
0xb9f4b9fe,0xbac7bae9,0xb9dfb9e9,0xba7ebaa3,0xb9c9b9d4,0xba2dba56,0xb9b3b9be,0xb9d6ba02,0xb99db9a8,0xb979b9a8,0xb986b992,0xb916b948,0xb970b97b,0xb8adb8e2,0xb958b964,0xb840b877,
0x39373927,0x381a37b7,0x39583948,0x38943858,0x39793969,0x390738ce,0x39993989,0x3974393e,0x39b839a8,0x39da39a8,0x39d639c7,0x3a393a0b,0x39f439e5,0x3a903a65,0x3a113a02,0x3ade3ab8,
0x3a2d3a3f,0x3af43b1a,0x3a093a1b,0x3aa23acc,0x39e339f6,0x3a453a74,0x39bc39d0,0x39df3a13,0x399439a8,0x397039a8,0x396b3980,0x38f83935,0x39413956,0x387a38ba,0x3916392b,0x37e83838,
0xb8f3b8d8,0xb79bb705,0xb929b90e,0xb85fb817,0xb95db943,0xb8eab8a6,0xb990b976,0xb96bb92b,0xb9c0b9a8,0xb9e3b9a8,0xb9f0b9d8,0xba50ba1b,0xba1dba07,0xbab3ba83,0xba49ba33,0xbb0abae0,
0xba64ba7c,0xbb1ebb46,0xba31ba4b,0xbac4baf3,0xb9fcba17,0xba5cba92,0xb9c5b9e1,0xb9e7ba23,0xb98bb9a8,0xb966b9a8,0xb94fb96d,0xb8dbb922,0xb911b930,0xb845b891,0xb8d1b8f1,0xb74eb7ee,
0x38ad3887,0x36ff364e,0x38f838d3,0x382a37ac,0x3941391d,0x38cc387c,0x39863964,0x39623918,0x39c939a8,0x39eb39a8,0x3a0939e9,0x3a673a2b,0x3a453a27,0x3ad53aa0,0x3a7e3a62,0x3b323b05,
0x3b453b6e,0x3bbc3bdd,0x3ae53b17,0x3b573b8f,0x3a733aae,0x3ac73b14,0x39f03a33,0x3a113a71,0x395d39a8,0x393739a8,0x38bc390e,0x384038bf,0x380f3867,0x365f3775,0x36af376a,0x341a3540,
0xb65fb593,0xb389b115,0xb7e8b726,0xb625b4f9,0xb8adb852,0xb830b748,0xb958b905,0xb933b8b5,0xb9f4b9a8,0xba15b9a8,0xba7eba3b,0xbad1ba78,0xbaf4babc,0xbb63bb20,0xbb57bb28,0xbbc6bb9b,
0xbb68bb91,0xbbd0bbed,0xbb04bb39,0xbb6fbba6,0xba89bac9,0xbadbbb2b,0xb9f8ba43,0xba19ba7f,0xb954b9a8,0xb92eb9a8,0xb89eb8fb,0xb820b8ab,0xb7b2b83d,0xb5ebb71b,0xb60eb6e3,0xb2deb4b1,
0x35bc34d5,0x32322f0e,0x377a369e,0x35b13469,0x388e3828,0x380f36ee,0x394f38f1,0x392938a0,0x39fc39a8,0x3a1d39a8,0x3a933a4b,0x3ae53a87,0x3b133ad6,0x3b7a3b36,0x3b783b49,0x3bd93bb1,
0x3b873baf,0x3be13bf8,0x3b213b58,0x3b853bbb,0x3a9e3ae3,0x3aee3b41,0x3a003a52,0x3a213a8e,0x394a39a8,0x392439a8,0x387f38e7,0x37fe3896,0x37423812,0x357636c1,0x356a3659,0x31853420,
0xb517b414,0xb0d7abd9,0xb70ab614,0xb53ab3ae,0xb86fb7f9,0xb7ddb693,0xb946b8dd,0xb91fb88c,0xba04b9a8,0xba25b9a8,0xbaa9ba5a,0xbaf7ba95,0xbb2fbaf0,0xbb90bb4b,0xbb96bb67,0xbbe8bbc4,
0xbba3bbc9,0xbbefbbff,0xbb3dbb74,0xbb9abbcd,0xbab3bafc,0xbb01bb55,0xba09ba62,0xba29ba9c,0xb941b9a8,0xb91bb9a8,0xb85fb8d3,0xb7bdb881,0xb6d2b7cd,0xb4ffb665,0xb4c3b5ce,0xb029b31b,
0x346f32a1,0x2ef52248,0x36993587,0x34c33288,0x385037a1,0x379b3637,0x393c38c9,0x39163877,0x3a0d39a8,0x3a2d39a8,0x3abd3a69,0x3b0a3aa3,0x3b4a3b08,0x3ba33b5f,0x3bb03b82,0x3bf43bd5,
0x3bf83c00,0x3bf93bd4,0x3bac3bdc,0x3be43bfe,0x3b133b69,0x3b543bab,0x3a313aaa,0x3a503ae0,0x391139a8,0x38ea39a8,0x377a386d,0x366b3817,0x34873608,0x313b348d,0x2d9731f4,0xad65291b,
0xac3828b6,0x2ec33365,0xb44bb160,0xb0bea57f,0xb759b5da,0xb648b45d,0xb90cb862,0xb8e5b80d,0xba35b9a8,0xba54b9a8,0xbb1bbab1,0xbb5cbae6,0xbbb5bb72,0xbbe9bbb2,0xbbfcbbe3,0xbbf5bc00,
0xbbfebbfc,0xbbefbbbc,0xbbbdbbe9,0xbbeebc00,0xbb24bb7b,0xbb63bbb9,0xba39bab8,0xba58baed,0xb907b9a8,0xb8e0b9a8,0xb737b858,0xb625b802,0xb40eb5ab,0xb042b42c,0xa9b1b0cb,0x30109a48,
0x25e4ad7e,0xb0beb475,0x33a23036,0x2f8ba3db,0x3715357c,0x360233f7,0x3902384d,0x38db37ee,0x3a3d39a8,0x3a5c39a8,0x3b2c3abf,0x3b6a3af3,0x3bc53b84,0x3bf23bc0,0x3bff3bee,0x3be93c00,
0x3c003bf4,0x3be23ba0,0x3bcc3bf3,0x3bf53bff,0x3b353b8c,0x3b713bc6,0x3a413ac6,0x3a603af9,0x38fd39a8,0x38d639a8,0x36f43842,0x35df37d8,0x3328354c,0x2e913396,0x16482f40,0xb16ca852,
0x251b304e,0x32193534,0xb2adae14,0xad972aac,0xb6d2b51d,0xb5bcb334,0xb8f8b838,0xb8d1b7c2,0xba45b9a8,0xba64b9a8,0xbb3dbacc,0xbb78baff,0xbbd3bb95,0xbbf8bbcb,0xbc00bbf7,0xbbdabbfd,
0xbbfebbe6,0xbbd2bb80,0xbbd9bbfa,0xbbfbbbfb,0xbb45bb9d,0xbb7fbbd1,0xba49bad3,0xba67bb05,0xb8f3b9a8,0xb8ccb9a8,0xb6afb82d,0xb599b7ac,0xb232b4ed,0xac9cb2d2,0x294dace7,0x32c62c83,
0xac06b1db,0xb371b5f1,0x31b62b75,0x2b43adb0,0x368d34bd,0x3576326f,0x38ee3822,0x38c73796,0x3a4d39a8,0x3a6b39a8,0x3b4c3ad9,0x3b853b0b,0x3bdf3ba4,0x3bfd3bd6,0x3bfc3bfd,0x3bc83bf8,
0x3bbd3b5a,0x3b473a99,0x3bfe3bf4,0x3bf93bbe,0x3b8b3bdb,0x3bb83bf7,0x3a6f3b11,0x3a8c3b3e,0x38c139a8,0x389939a8,0x35523780,0x343236cc,0x294d320d,0xad332de2,0xb40eaedc,0xb6a4b408,
0x346336aa,0x36f438b0,0xa6ad3004,0x2e2d3451,0xb52fb1aa,0xb40ead1a,0xb8bcb76a,0xb894b6b5,0xba73b9a8,0xba90b9a8,0xbb92bb17,0xbbbdbb43,0xbbffbbe0,0xbbf6bbf9,0xbbb2bbf0,0xbb35bbb4,
0xbba5bb30,0xbb21ba5e,0xbc00bbeb,0xbbf3bbaa,0xbb98bbe4,0xbbc2bbfb,0xba76bb1d,0xba93bb49,0xb8b7b9a8,0xb88eb9a8,0xb50bb753,0xb3d3b69e,0xa17fb147,0x2f27ac51,0x34b73099,0x37423499,
0xb50bb75e,0xb790b900,0x9cb6b12e,0xb010b4e1,0x34e730e4,0x33892b11,0x38b2373d,0x38893687,0x3a7a39a8,0x3a9739a8,0x3b9e3b22,0x3bc63b4e,0x3c003be8,0x3bef3bfd,0x3b983be5,0x3b0d3b9e,
0x3b893b02,0x3af73a1f,0x3c003bdf,0x3beb3b93,0x3ba33bec,0x3bcb3bfe,0x3a7e3b28,0x3a9b3b53,0x38ad39a8,0x388439a8,0x34c33726,0x33403670,0xa51b3080,0xb08d297f,0xb55eb1c3,0xb7ddb529,
0x35b13807,0x3815394d,0x28843257,0x31093570,0xb49fb01d,0xb2f7a7da,0xb8a8b710,0xb87fb659,0xba81b9a8,0xba9eb9a8,0xbba9bb2e,0xbbcfbb58,0xbbffbbef,0xbbe6bbff,0xbb7abbd7,0xbae1bb86,
0xbb6abad0,0xbacbb9dc,0xbbfdbbd0,0xbbe1bb79,0xbbaebbf2,0xbbd3bc00,0xba85bb33,0xbaa2bb5d,0xb8a3b9a8,0xb87ab9a8,0xb47bb6f9,0xb2adb642,0x2a7aaf72,0x3185a4b6,0x360232ea,0x383a35b6,
0xb654b85d,0xb85fb996,0xac38b37d,0xb201b5fd,0x34572eaa,0x32631e48,0x389e36e3,0x3874362b,0x3a8939a8,0x3aa539a8,0x3bb33b39,0x3bd73b62,0x3bfc3bf5,0x3bdc3c00,0x3b593bc7,0x3ab33b6b,
0x39b739b9,0x3a883aa6,0x39b239b4,0x3a483a68,0x39ae39b0,0x3a033a26,0x39a939ab,0x39bb39e0,0x39a539a7,0x396e3995,0x39a039a3,0x391e3947,0x399c399e,0x38ca38f5,0x3997399a,0x3873389f,
0xb97cb975,0xb87eb84c,0xb98ab983,0xb8deb8ae,0xb997b991,0xb93bb90d,0xb9a5b99e,0xb993b967,0xb9b2b9ab,0xb9e6b9bd,0xb9bfb9b9,0xba34ba0e,0xb9ccb9c6,0xba7dba59,0xb9d9b9d3,0xbac0ba9f,
0xb9efb9f9,0xbab6bad9,0xb9d9b9e4,0xba6aba91,0xb9c4b9cf,0xba18ba42,0xb9aeb9b9,0xb9bfb9ec,0xb997b9a3,0xb961b991,0xb981b98c,0xb8fcb92f,0xb96ab975,0xb892b8c8,0xb953b95e,0xb824b85c,
0x3940392f,0x383937f6,0x39613950,0x38b13876,0x39813971,0x392338eb,0x39a03991,0x398e395a,0x39bf39b0,0x39f339c1,0x39de39cf,0x3a4f3a22,0x39fb39ec,0x3aa43a7b,0x3a183a0a,0x3af03acb,
0x3a243a36,0x3ae13b07,0x39ff3a12,0x3a8b3ab7,0x39d939ec,0x3a2c3a5d,0x39b239c6,0x39c439f9,0x398a399e,0x3953398c,0x39613975,0x38d93917,0x3936394b,0x3859389a,0x390b3921,0x37a43816,
0xb901b8e6,0xb7e6b750,0xb936b91c,0xb883b83c,0xb96ab950,0xb90bb8c8,0xb99cb983,0xb98ab94b,0xb9ccb9b4,0xb9ffb9c6,0xb9fbb9e4,0xba6aba36,0xba28ba12,0xbacaba9b,0xba53ba3e,0xbb1dbaf5,
0xba57ba70,0xbb09bb33,0xba24ba3e,0xbaabbadc,0xb9efba0a,0xba40ba77,0xb9b7b9d3,0xb9c8ba05,0xb97cb99a,0xb944b988,0xb940b95e,0xb8b6b8fe,0xb901b921,0xb81eb86b,0xb8c0b8e1,0xb6fcb79e,
0x38c0389a,0x375636a7,0x390b38e6,0x38543800,0x3953392f,0x38f238a4,0x39973975,0x3985393d,0x39d939b9,0x3a0c39ca,0x3a1839f9,0x3a843a4a,0x3a533a36,0x3aed3abb,0x3a8b3a70,0x3b473b1c,
0x3b2e3b5a,0x3ba63bce,0x3aca3afe,0x3b373b74,0x3a533a91,0x3a9d3aef,0x39cc3a12,0x39de3a42,0x39363983,0x38fc3971,0x389238e6,0x37fb3880,0x37c5383c,0x35d136eb,0x3651370d,0x330934ae,
0xb6c3b5fa,0xb460b251,0xb824b788,0xb6b8b590,0xb8d9b880,0xb873b7d5,0xb981b92f,0xb96eb8f5,0xba18b9cf,0xba48b9e0,0xba9dba5d,0xbafabaa6,0xbb0fbad9,0xbb80bb43,0xbb6cbb40,0xbbd8bbb2,
0xbb51bb7d,0xbbbdbbe0,0xbae7bb1f,0xbb4ebb8c,0xba66baa9,0xbaafbb04,0xb9d1ba1e,0xb9e2ba4e,0xb928b97e,0xb8edb96c,0xb86eb8cd,0xb7afb866,0xb74bb80b,0xb54fb684,0xb5a2b679,0xb197b411,
0x362e3549,0x338330de,0x37e6370d,0x3651350e,0x38c0385c,0x38593788,0x397c3921,0x396a38e6,0x3a2439d3,0x3a5339e4,0x3ab63a70,0x3b0f3ab7,0x3b2e3af5,0x3b973b5a,0x3b8d3b61,0x3be83bc7,
0x3b703b9c,0x3bd03bef,0x3b033b3d,0x3b653ba2,0x3a793ac1,0x3ac03b19,0x39d53a2a,0x39e63a59,0x3919397a,0x38de3967,0x384938b4,0x3761384c,0x36cf37b4,0x34cc361d,0x34f035e2,0x302332e4,
0xb596b496,0xb244aecf,0xb783b690,0xb5e8b48a,0xb8a7b836,0xb83eb73a,0xb978b912,0xb965b8d7,0xba30b9d7,0xba5fb9e8,0xbacdba82,0xbb23bac8,0xbb4cbb10,0xbbacbb6f,0xbbaabb7f,0xbbf4bbd8,
0xbb8dbbb7,0xbbe0bbf9,0xbb1dbb5a,0xbb7abbb5,0xba8bbad9,0xbad0bb2d,0xb9d9ba36,0xb9eaba65,0xb90bb975,0xb8cfb963,0xb824b89a,0xb713b831,0xb651b750,0xb447b5b3,0xb43bb549,0xad58b1a4,
0x34fc33c0,0x31032bc0,0x371e3611,0x357e3405,0x388d3811,0x382436eb,0x39733903,0x396138c8,0x3a3c39db,0x3a6a39ec,0x3ae43a94,0x3b373ad9,0x3b673b2a,0x3bbe3b83,0x3bc33b9a,0x3bfc3be7,
0x3bed3bff,0x3bff3bea,0x3b8d3bc7,0x3bcc3bf5,0x3ae13b40,0x3b1d3b83,0x39ef3a70,0x39ff3a9b,0x38c0395e,0x3883394b,0x36c33816,0x357e3750,0x33833549,0x2e84332e,0x28cf3061,0xb0aca5b2,
0xaf7ea376,0x29663166,0xb514b2fd,0xb2bfad71,0xb809b69b,0xb734b555,0xb95cb8b9,0xb949b87b,0xba75b9f1,0xbaa1ba01,0xbb49bae9,0xbb8bbb25,0xbbcfbb96,0xbbf9bbd2,0xbc00bbf2,0xbbe3bbfe,
0xbbf6bc00,0xbbfcbbda,0xbb9fbbd6,0xbbd8bbfb,0xbaf0bb52,0xbb2cbb92,0xb9f3ba7b,0xba03baa6,0xb8b1b95a,0xb873b947,0xb673b7f6,0xb52cb718,0xb276b4de,0xac5eb251,0x2052ae39,0x321f2bf2,
0x2cf4a806,0xad3fb2d8,0x34a831ee,0x31e22a93,0x37db364b,0x36fc3502,0x395738a9,0x3944386b,0x3a8039f5,0x3aab3a05,0x3b5b3af8,0x3b993b33,0x3bdd3ba7,0x3bfd3bdd,0x3bff3bfa,0x3bd13bf9,
0x3bfd3bfd,0x3bf53bc6,0x3baf3be3,0x3be23bff,0x3b003b64,0x3b393ba0,0x39f73a86,0x3a083ab0,0x38a23955,0x38633942,0x362237bf,0x34d836e0,0x31663472,0x286b3172,0xaaf82b5c,0xb390ae84,
0xa8cf2cf4,0x2fc93423,0xb43bb0de,0xb103a484,0xb7a4b5fa,0xb6c3b4ae,0xb953b89a,0xb940b85c,0xba8bb9f9,0xbab6ba0a,0xbb6cbb07,0xbba6bb40,0xbbe8bbb7,0xbc00bbe7,0xbbfabbff,0xbbbabbf1,
0xbc00bbf6,0xbbebbbae,0xbbbebbed,0xbbebbc00,0xbb0fbb74,0xbb47bbad,0xb9fbba91,0xba0cbabb,0xb892b950,0xb854b93d,0xb5d1b788,0xb484b6a7,0xb055b405,0x9248b093,0x2e6ba484,0x347e3086,
0x98b6afe2,0xb128b4d8,0x339c2f97,0x3023a420,0x376c35a8,0x368a345a,0x394e388b,0x393b384c,0x3a9639fd,0x3ac03a0e,0x3b7c3b16,0x3bb33b4d,0x3bf23bc5,0x3c003bef,0x3bf03c00,0x3ba03be5,
0x3bde3b91,0x3b8a3af7,0x3bf23bff,0x3c003be3,0x3b533bb9,0x3b823bdf,0x3a103ac5,0x3a203aec,0x38443939,0x38033925,0x342f366d,0x31b03584,0xa8392f65,0xb15a1d7f,0xb531b1c9,0xb7e0b55b,
0x3269358a,0x35a83819,0xae842a61,0x205231e2,0xb651b405,0xb567b15a,0xb936b83c,0xb923b7f6,0xbacaba12,0xbaf0ba22,0xbbbebb5a,0xbbe3bb88,0xbbfdbbf5,0xbbddbc00,0xbb81bbd6,0xbadfbb7c,
0xbbcebb70,0xbb6dbac6,0xbbf8bbfb,0xbbffbbd6,0xbb60bbc4,0xbb8dbbe7,0xba14bacf,0xba24baf5,0xb834b934,0xb7e6b921,0xb3b4b634,0xb103b549,0x2c44ada3,0x326925b2,0x35e23309,0x384135f4,
0xb3a8b63a,0xb63fb869,0x2cc2ad58,0xa89db2f0,0x3617335f,0x352c30ac,0x3931382c,0x391e37d5,0x3ad43a16,0x3afa3a26,0x3bc93b66,0x3bea3b92,0x3bf93bfa,0x3bcf3bff,0x3b5f3bc5,0x3aad3b5d,
0x3bba3b4c,0x3b4d3a93,0x3bfc3bf6,0x3bfd3bc7,0x3b6c3bce,0x3b973bed,0x3a183ad9,0x3a283afe,0x3824392f,0x37c5391c,0x330935fa,0x3055350e,0xae6b2bc0,0xb377aa61,0xb690b423,0xb890b68a,
0x347236e5,0x36d438b6,0xa9fd2f7e,0x2c1233fd,0xb5dcb2b3,0xb4f0affb,0xb92db81c,0xb919b7b4,0xbaddba1a,0xbb03ba2a,0xbbd3bb72,0xbbf0bb9c,0xbbf2bbfe,0xbbbfbbfc,0xbb38bbaf,0xba77bb3c,
0xbba4bb23,0xbb2aba5b,0xbbffbbee,0xbbfabbb6,0xbb77bbd7,0xbba1bbf3,0xba1cbae2,0xba2cbb07,0xb813b92a,0xb7a4b917,0xb25db5bf,0xaf4cb4d2,0x3048a839,0x34412cf4,0x373a34c0,0x38dc371e,
0xb50eb78e,0xb767b901,0x24e9b0d1,0xadd5b484,0x35a23207,0x34b42e9d,0x3928380b,0x39143793,0x3ae73a1e,0x3b0c3a2e,0x3bdb3b7d,0x3bf53ba6,0x3be93c00,0x3bad3bf7,0x3b0d3b97,0x3a3e3b18,
0xb999b996,0xb889b85d,0xb99db99b,0xb8e0b8b5,0xb9a1b99f,0xb933b909,0xb9a6b9a4,0xb982b95b,0xb9aab9a8,0xb9cdb9a8,0xb9afb9ad,0xba15b9f2,0xb9b3b9b1,0xba58ba37,0xb9b8b9b5,0xba97ba78,
0xb9d6b9dc,0xbab0bad0,0xb9c9b9d0,0xba6bba8e,0xb9bcb9c3,0xba21ba47,0xb9afb9b5,0xb9d2b9fa,0xb9a1b9a8,0xb97db9a8,0xb994b99b,0xb924b951,0xb986b98d,0xb8c7b8f6,0xb979b980,0xb865b896,
0x3958394d,0x38403807,0x39703964,0x38ad3877,0x3986397b,0x391638e2,0x399d3992,0x39793948,0x39b339a8,0x39d639a8,0x39c939be,0x3a2d3a02,0x39df39d4,0x3a7e3a56,0x39f439e9,0x3ac73aa3,
0x3a113a1f,0x3ade3b02,0x39f43a02,0x3a903ab8,0x39d639e5,0x3a393a65,0x39b839c7,0x39da3a0b,0x399939a8,0x397439a8,0x39793989,0x3907393e,0x39583969,0x389438ce,0x39373948,0x381a3858,
0xb916b900,0xb7e8b75e,0xb941b92b,0xb87ab838,0xb96bb956,0xb8f8b8ba,0xb994b980,0xb970b935,0xb9bcb9a8,0xb9dfb9a8,0xb9e3b9d0,0xba45ba13,0xba09b9f6,0xbaa2ba74,0xba2dba1b,0xbaf4bacc,
0xba49ba5e,0xbb0abb30,0xba1dba33,0xbab3bae0,0xb9f0ba07,0xba50ba83,0xb9c0b9d8,0xb9e3ba1b,0xb990b9a8,0xb96bb9a8,0xb95db976,0xb8eab92b,0xb929b943,0xb85fb8a6,0xb8f3b90e,0xb79bb817,
0x38d138b0,0x374e36aa,0x391138f1,0x384537ee,0x394f3930,0x38db3891,0x398b396d,0x39663922,0x39c539a8,0x39e739a8,0x39fc39e1,0x3a5c3a23,0x3a313a17,0x3ac43a92,0x3a643a4b,0x3b1e3af3,
0x3a7e3a99,0x3b323b5a,0x3a453a62,0x3ad53b05,0x3a093a27,0x3a673aa0,0x39c939e9,0x39eb3a2b,0x398639a8,0x396239a8,0x39413964,0x38cc3918,0x38f8391d,0x382a387c,0x38ad38d3,0x36ff37ac,
0xb6afb5f1,0xb41ab1db,0xb80fb76a,0xb65fb540,0xb8bcb867,0xb840b775,0xb95db90e,0xb937b8bf,0xb9f0b9a8,0xba11b9a8,0xba73ba33,0xbac7ba71,0xbae5baae,0xbb57bb14,0xbb45bb17,0xbbbcbb8f,
0xbb57bb80,0xbbc6bbe6,0xbaf4bb28,0xbb63bb9b,0xba7ebabc,0xbad1bb20,0xb9f4ba3b,0xba15ba78,0xb958b9a8,0xb933b9a8,0xb8adb905,0xb830b8b5,0xb7e8b852,0xb625b748,0xb65fb726,0xb389b4f9,
0x360e3534,0x32de304e,0x37b236e3,0x35eb34b1,0x389e383d,0x3820371b,0x395438fb,0x392e38ab,0x39f839a8,0x3a1939a8,0x3a893a43,0x3adb3a7f,0x3b043ac9,0x3b6f3b2b,0x3b683b39,0x3bd03ba6,
0x3b783ba0,0x3bd93bf4,0x3b133b49,0x3b7a3bb1,0x3a933ad6,0x3ae53b36,0x39fc3a4b,0x3a1d3a87,0x394f39a8,0x392939a8,0x388e38f1,0x380f38a0,0x377a3828,0x35b136ee,0x35bc369e,0x32323469,
0xb56ab475,0xb185ad7e,0xb742b659,0xb576b420,0xb87fb812,0xb7feb6c1,0xb94ab8e7,0xb924b896,0xba00b9a8,0xba21b9a8,0xba9eba52,0xbaeeba8e,0xbb21bae3,0xbb85bb41,0xbb87bb58,0xbbe1bbbb,
0xbb96bbbc,0xbbe8bbfc,0xbb2fbb67,0xbb90bbc4,0xbaa9baf0,0xbaf7bb4b,0xba04ba5a,0xba25ba95,0xb946b9a8,0xb91fb9a8,0xb86fb8dd,0xb7ddb88c,0xb70ab7f9,0xb53ab693,0xb517b614,0xb0d7b3ae,
0x34c33365,0x302928b6,0x36d235ce,0x34ff331b,0x385f37cd,0x37bd3665,0x394138d3,0x391b3881,0x3a0939a8,0x3a2939a8,0x3ab33a62,0x3b013a9c,0x3b3d3afc,0x3b9a3b55,0x3ba33b74,0x3bef3bcd,
0x3bb03bd4,0x3bf43c00,0x3b4a3b82,0x3ba33bd5,0x3abd3b08,0x3b0a3b5f,0x3a0d3a69,0x3a2d3aa3,0x393c39a8,0x391639a8,0x385038c9,0x379b3877,0x369937a1,0x34c33637,0x346f3587,0x2ef53288,
0xad972248,0x2d6532a1,0xb487b1f4,0xb13ba91b,0xb77ab608,0xb66bb48d,0xb911b86d,0xb8eab817,0xba31b9a8,0xba50b9a8,0xbb13baaa,0xbb54bae0,0xbbacbb69,0xbbe4bbab,0xbbf8bbdc,0xbbf9bbfe,
0xbbfcbbff,0xbbf5bbc9,0xbbb5bbe3,0xbbe9bc00,0xbb1bbb72,0xbb5cbbb2,0xba35bab1,0xba54bae6,0xb90cb9a8,0xb8e5b9a8,0xb759b862,0xb648b80d,0xb44bb5da,0xb0beb45d,0xac38b160,0x2ec3a57f,
0x29b1abd9,0xb010b414,0x340e30cb,0x30421a48,0x373735ab,0x3625342c,0x39073858,0x38e03802,0x3a3939a8,0x3a5839a8,0x3b243ab8,0x3b633aed,0x3bbd3b7b,0x3bee3bb9,0x3bfe3be9,0x3bef3c00,
0x3bff3bf8,0x3be93baf,0x3bc53bee,0x3bf23c00,0x3b2c3b84,0x3b6a3bc0,0x3a3d3abf,0x3a5c3af3,0x390239a8,0x38db39a8,0x3715384d,0x360237ee,0x33a2357c,0x2f8b33f7,0x25e43036,0xb0bea3db,
0x96482f0e,0x316c34d5,0xb328af40,0xae912852,0xb6f4b54c,0xb5dfb396,0xb8fdb842,0xb8d6b7d8,0xba41b9a8,0xba60b9a8,0xbb35bac6,0xbb71baf9,0xbbccbb8c,0xbbf5bbc6,0xbc00bbf3,0xbbe2bbff,
0xbc00bbed,0xbbdabb91,0xbbd3bbf7,0xbbf8bbfd,0xbb3dbb95,0xbb78bbcb,0xba45bacc,0xba64baff,0xb8f8b9a8,0xb8d1b9a8,0xb6d2b838,0xb5bcb7c2,0xb2adb51d,0xad97b334,0x251bae14,0x32192aac,
0xa94db115,0xb2c6b593,0x32322ce7,0x2c9cac83,0x36af34ed,0x359932d2,0x38f3382d,0x38cc37ac,0x3a4939a8,0x3a6739a8,0x3b453ad3,0x3b7f3b05,0x3bd93b9d,0x3bfb3bd1,0x3bfe3bfa,0x3bd23bfb,
0x3bfc3bdd,0x3bc83b6e,0x3bdf3bfd,0x3bfd3bf8,0x3b4c3ba4,0x3b853bd6,0x3a4d3ad9,0x3a6b3b0b,0x38ee39a8,0x38c739a8,0x368d3822,0x35763796,0x31b634bd,0x2b43326f,0xac062b75,0xb371adb0,
0x340e364e,0x36a43887,0xa94d2edc,0x2d333408,0xb552b20d,0xb432ade2,0xb8c1b780,0xb899b6cc,0xba6fb9a8,0xba8cb9a8,0xbb8bbb11,0xbbb8bb3e,0xbbfebbdb,0xbbf9bbf7,0xbbbdbbf4,0xbb47bbbe,
0xbbb2bb46,0xbb35ba7c,0xbbffbbf0,0xbbf6bbb4,0xbb92bbe0,0xbbbdbbf9,0xba73bb17,0xba90bb43,0xb8bcb9a8,0xb894b9a8,0xb52fb76a,0xb40eb6b5,0xa6adb1aa,0x2e2dad1a,0x34633004,0x36f43451,
0xb4b7b705,0xb742b8d8,0x217fb099,0xaf27b499,0x350b3147,0x33d32c51,0x38b73753,0x388e369e,0x3a7639a8,0x3a9339a8,0x3b983b1d,0x3bc23b49,0x3c003be4,0x3bf33bfb,0x3ba53beb,0x3b213baa,
0x3b983b1a,0x3b0d3a3f,0x3c003be5,0x3bef3b9e,0x3b9e3be8,0x3bc63bfd,0x3a7a3b22,0x3a973b4e,0x38b239a8,0x388939a8,0x34e7373d,0x33893687,0x9cb630e4,0xb0102b11,0xb50bb12e,0xb790b4e1,
0x355e37b7,0x37dd3927,0x251b31c3,0x308d3529,0xb4c3b080,0xb340a97f,0xb8adb726,0xb884b670,0xba7eb9a8,0xba9bb9a8,0xbba3bb28,0xbbcbbb53,0xbc00bbec,0xbbebbbfe,0xbb89bbdf,0xbaf7bb93,
0xbb7abae9,0xbae1b9fe,0xbbffbbd7,0xbbe6bb86,0xbba9bbef,0xbbcfbbff,0xba81bb2e,0xba9ebb58,0xb8a8b9a8,0xb87fb9a8,0xb49fb710,0xb2f7b659,0x2884b01d,0x3109a7da,0x35b13257,0x38153570,
0xb602b832,0xb83ab972,0xaa7ab2ea,0xb185b5b6,0x347b2f72,0x32ad24b6,0x38a336f9,0x387a3642,0x3a8539a8,0x3aa239a8,0x3bae3b33,0x3bd33b5d,0x3bfd3bf2,0x3be13c00,0x3b6a3bd0,0x3acb3b79,
0x3b593ab5,0x3ab339ba,0x3bfc3bc7,0x3bdc3b6b,0x3bb33bf5,0x3bd73c00,0x3a893b39,0x3aa53b62,0x389e39a8,0x387439a8,0x345736e3,0x3263362b,0xac382eaa,0xb2011e48,0xb654b37d,0xb85fb5fd,
0xb99ab997,0xb89fb873,0xb99eb99c,0xb8f5b8ca,0xb9a3b9a0,0xb947b91e,0xb9a7b9a5,0xb995b96e,0xb9abb9a9,0xb9e0b9bb,0xb9b0b9ae,0xba26ba03,0xb9b4b9b2,0xba68ba48,0xb9b9b9b7,0xbaa6ba88,
0xb9d3b9d9,0xba9fbac0,0xb9c6b9cc,0xba59ba7d,0xb9b9b9bf,0xba0eba34,0xb9abb9b2,0xb9bdb9e6,0xb99eb9a5,0xb967b993,0xb991b997,0xb90db93b,0xb983b98a,0xb8aeb8de,0xb975b97c,0xb84cb87e,
0x395e3953,0x385c3824,0x3975396a,0x38c83892,0x398c3981,0x392f38fc,0x39a33997,0x39913961,0x39b939ae,0x39ec39bf,0x39cf39c4,0x3a423a18,0x39e439d9,0x3a913a6a,0x39f939ef,0x3ad93ab6,
0x3a0a3a18,0x3acb3af0,0x39ec39fb,0x3a7b3aa4,0x39cf39de,0x3a223a4f,0x39b039bf,0x39c139f3,0x399139a0,0x395a398e,0x39713981,0x38eb3923,0x39503961,0x387638b1,0x392f3940,0x37f63839,
0xb921b90b,0xb816b7a4,0xb94bb936,0xb89ab859,0xb975b961,0xb917b8d9,0xb99eb98a,0xb98cb953,0xb9c6b9b2,0xb9f9b9c4,0xb9ecb9d9,0xba5dba2c,0xba12b9ff,0xbab7ba8b,0xba36ba24,0xbb07bae1,
0xba3eba53,0xbaf5bb1d,0xba12ba28,0xba9bbaca,0xb9e4b9fb,0xba36ba6a,0xb9b4b9cc,0xb9c6b9ff,0xb983b99c,0xb94bb98a,0xb950b96a,0xb8c8b90b,0xb91cb936,0xb83cb883,0xb8e6b901,0xb750b7e6,
0x38e138c0,0x379e36fc,0x39213901,0x386b381e,0x395e3940,0x38fe38b6,0x399a397c,0x39883944,0x39d339b7,0x3a0539c8,0x3a0a39ef,0x3a773a40,0x3a3e3a24,0x3adc3aab,0x3a703a57,0x3b333b09,
0x3a703a8b,0x3b1c3b47,0x3a363a53,0x3abb3aed,0x39f93a18,0x3a4a3a84,0x39b939d9,0x39ca3a0c,0x39753997,0x393d3985,0x392f3953,0x38a438f2,0x38e6390b,0x38003854,0x389a38c0,0x36a73756,
0xb70db651,0xb4aeb309,0xb83cb7c5,0xb6ebb5d1,0xb8e6b892,0xb880b7fb,0xb983b936,0xb971b8fc,0xba12b9cc,0xba42b9de,0xba91ba53,0xbaefba9d,0xbafebaca,0xbb74bb37,0xbb5abb2e,0xbbcebba6,
0xbb40bb6c,0xbbb2bbd8,0xbad9bb0f,0xbb43bb80,0xba5dba9d,0xbaa6bafa,0xb9cfba18,0xb9e0ba48,0xb92fb981,0xb8f5b96e,0xb880b8d9,0xb7d5b873,0xb788b824,0xb590b6b8,0xb5fab6c3,0xb251b460,
0x367935a2,0x34113197,0x380b374b,0x3684354f,0x38cd386e,0x386637af,0x397e3928,0x396c38ed,0x3a1e39d1,0x3a4e39e2,0x3aa93a66,0x3b043aaf,0x3b1f3ae7,0x3b8c3b4e,0x3b7d3b51,0x3be03bbd,
0x3b613b8d,0x3bc73be8,0x3af53b2e,0x3b5a3b97,0x3a703ab6,0x3ab73b0f,0x39d33a24,0x39e43a53,0x3921397c,0x38e6396a,0x385c38c0,0x37883859,0x370d37e6,0x350e3651,0x3549362e,0x30de3383,
0xb5e2b4f0,0xb2e4b023,0xb7b4b6cf,0xb61db4cc,0xb8b4b849,0xb84cb761,0xb97ab919,0xb967b8de,0xba2ab9d5,0xba59b9e6,0xbac1ba79,0xbb19bac0,0xbb3dbb03,0xbba2bb65,0xbb9cbb70,0xbbefbbd0,
0xbb7fbbaa,0xbbd8bbf4,0xbb10bb4c,0xbb6fbbac,0xba82bacd,0xbac8bb23,0xb9d7ba30,0xb9e8ba5f,0xb912b978,0xb8d7b965,0xb836b8a7,0xb73ab83e,0xb690b783,0xb48ab5e8,0xb496b596,0xaecfb244,
0x3549343b,0x31a42d58,0x37503651,0x35b33447,0x389a3824,0x38313713,0x3975390b,0x396338cf,0x3a3639d9,0x3a6539ea,0x3ad93a8b,0x3b2d3ad0,0x3b5a3b1d,0x3bb53b7a,0x3bb73b8d,0x3bf93be0,
0x3b9a3bc3,0x3be73bfc,0x3b2a3b67,0x3b833bbe,0x3a943ae4,0x3ad93b37,0x39db3a3c,0x39ec3a6a,0x39033973,0x38c83961,0x3811388d,0x36eb3824,0x3611371e,0x3405357e,0x33c034fc,0x2bc03103,
0xb061a8cf,0x25b230ac,0xb549b383,0xb32eae84,0xb816b6c3,0xb750b57e,0xb95eb8c0,0xb94bb883,0xba70b9ef,0xba9bb9ff,0xbb40bae1,0xbb83bb1d,0xbbc7bb8d,0xbbf5bbcc,0xbbffbbed,0xbbeabbff,
0xbbf2bc00,0xbbfebbe3,0xbb96bbcf,0xbbd2bbf9,0xbae9bb49,0xbb25bb8b,0xb9f1ba75,0xba01baa1,0xb8b9b95c,0xb87bb949,0xb69bb809,0xb555b734,0xb2fdb514,0xad71b2bf,0xa376af7e,0x31662966,
0x2e39a052,0xabf2b21f,0x34de3276,0x32512c5e,0x37f63673,0x3718352c,0x395a38b1,0x39473873,0x3a7b39f3,0x3aa63a03,0x3b523af0,0x3b923b2c,0x3bd63b9f,0x3bfb3bd8,0x3c003bf6,0x3bda3bfc,
0x3bfa3bff,0x3bf93bd1,0x3ba73bdd,0x3bdd3bfd,0x3af83b5b,0x3b333b99,0x39f53a80,0x3a053aab,0x38a93957,0x386b3944,0x364b37db,0x350236fc,0x31ee34a8,0x2a9331e2,0xa8062cf4,0xb2d8ad3f,
0xab5c2af8,0x2e843390,0xb472b166,0xb172a86b,0xb7bfb622,0xb6e0b4d8,0xb955b8a2,0xb942b863,0xba86b9f7,0xbab0ba08,0xbb64bb00,0xbba0bb39,0xbbe3bbaf,0xbbffbbe2,0xbbfdbbfd,0xbbc6bbf5,
0xbbffbbfa,0xbbf1bbba,0xbbb7bbe8,0xbbe7bc00,0xbb07bb6c,0xbb40bba6,0xb9f9ba8b,0xba0abab6,0xb89ab953,0xb85cb940,0xb5fab7a4,0xb4aeb6c3,0xb0deb43b,0xa484b103,0x2cf4a8cf,0x34232fc9,
0x2484ae6b,0xb086b47e,0x34053055,0x30931248,0x378835d1,0x36a73484,0x39503892,0x393d3854,0x3a9139fb,0x3abb3a0c,0x3b743b0f,0x3bad3b47,0x3bed3bbe,0x3c003beb,0x3bf63c00,0x3bae3beb,
0x3c003bf0,0x3be53ba0,0x3bc53bf2,0x3bef3c00,0x3b163b7c,0x3b4d3bb3,0x39fd3a96,0x3a0e3ac0,0x388b394e,0x384c393b,0x35a8376c,0x345a368a,0x2f97339c,0xa4203023,0xafe298b6,0xb4d8b128,
0x31c93531,0x355b37e0,0xaf652839,0x9d7f315a,0xb66db42f,0xb584b1b0,0xb939b844,0xb925b803,0xbac5ba10,0xbaecba20,0xbbb9bb53,0xbbdfbb82,0xbbffbbf2,0xbbe3bc00,0xbb91bbde,0xbaf7bb8a,
0xbbd6bb81,0xbb7cbadf,0xbbf5bbfd,0xbc00bbdd,0xbb5abbbe,0xbb88bbe3,0xba12baca,0xba22baf0,0xb83cb936,0xb7f6b923,0xb405b651,0xb15ab567,0x2a61ae84,0x31e22052,0x358a3269,0x381935a8,
0xb309b5e2,0xb5f4b841,0x2da3ac44,0xa5b2b269,0x363433b4,0x35493103,0x39343834,0x392137e6,0x3acf3a14,0x3af53a24,0x3bc43b60,0x3be73b8d,0x3bfb3bf8,0x3bd63bff,0x3b703bce,0x3ac63b6d,
0x3bc53b5f,0x3b5d3aad,0x3bfa3bf9,0x3bff3bcf,0x3b663bc9,0x3b923bea,0x3a163ad4,0x3a263afa,0x382c3931,0x37d5391e,0x335f3617,0x30ac352c,0xad582cc2,0xb2f0a89d,0xb63ab3a8,0xb869b63f,
0x34233690,0x368a3890,0xabc02e6b,0x2a613377,0xb5fab309,0xb50eb055,0xb92fb824,0xb91cb7c5,0xbad9ba18,0xbafeba28,0xbbcebb6c,0xbbedbb97,0xbbf6bbfc,0xbbc7bbfd,0xbb4cbbba,0xba93bb4d,
0xbbafbb38,0xbb3cba77,0xbbfebbf2,0xbbfcbbbf,0xbb72bbd3,0xbb9cbbf0,0xba1abadd,0xba2abb03,0xb81cb92d,0xb7b4b919,0xb2b3b5dc,0xaffbb4f0,0x2f7ea9fd,0x33fd2c12,0x36e53472,0x38b636d4,
0xb4c0b73a,0xb71eb8dc,0x2839b048,0xacf4b441,0x35bf325d,0x34d22f4c,0x392a3813,0x391737a4,0x3ae23a1c,0x3b073a2c,0x3bd73b77,0x3bf33ba1,0x3bee3bff,0x3bb63bfa,0x3b233ba4,0x3a5b3b2a,
0x3b973b0d,0x3b183a3e,0x3c003be9,0x3bf73bad,0x3b7d3bdb,0x3ba63bf5,0x3a1e3ae7,0x3a2e3b0c,0x380b3928,0x37933914,0x320735a2,0x2e9d34b4,0xb0d124e9,0xb484add5,0xb78eb50e,0xb901b767,
0xb97239ba,0x39dc3996,0xb8323ab5,0x3ad0385d,0x3927b9fe,0xba1fb94d,0x37b7bae9,0xbb02b807,0xb8d83a3f,0x3a5e3900,0xb7053b1a,0x3b30375e,0x3887ba7c,0xba99b8b0,0x364ebb46,0xbb5ab6aa,
0xb90039dc,0x3a3f3972,0xad7e3be6,0x3bf83115,0x3807ba99,0xbae9b887,0xabd9bc00,0xbbfca248,0xb5f13b30,0x3b6e3705,0x32a13bed,0x3bd4b04e,0x3365bba0,0xbbc9b4d5,0xb593bbaf,0xbb803475,
0xb88739fe,0x3a99394d,0x35f13bbc,0x3b6eb414,0x3593bb1a,0xbb80b75e,0xb8b0bb02,0xba7c37b7,0xaf0e3bc9,0x3bf43365,0x3a1f39dc,0x3927b972,0xb04ebc00,0xbbed2248,0xbb30b85d,0xb7053ab5,
0xb8073a1f,0x3ae93927,0x39fe3a3f,0x394db900,0x31dbbb80,0xbbddb593,0xbb6eb832,0xb5f13ad0,0x31153c00,0x3be62248,0x3bff32a1,0x28b6bbd4,0xb7b7bb91,0xbb023534,0xbba0304e,0x34d53bed,
0xb7053a3f,0x3b303900,0x3bbc375e,0x3414bb1a,0x2248bbc9,0xbc00b365,0xbbdda8b6,0x31db3bff,0x36aa3bd4,0x3b46b2a1,0x3a7cb64e,0xb8b0bb5a,0xba1fba5e,0xb92738d8,0xb7b739fe,0x3b02394d,
0xb5f13a5e,0x3b6e38d8,0x3bd42bd9,0xb2a1bbfc,0xb115bbf4,0xbbe6af0e,0xb9dc375e,0x39723b1a,0x39273b46,0x3a1fb6aa,0x3475bad0,0xbbafb832,0xbb91b887,0xb5343a99,0x34143c00,0x3bbc2248,
0xb4d53a7c,0x3ba038b0,0x3a3fb593,0xb900bb80,0xb534bc00,0xbb912248,0xb4143ab5,0x3bbc385d,0x3a993a5e,0x3887b8d8,0xb5f1bbfc,0xbb6e2bd9,0xbbffb475,0x28b63baf,0x3ad03a1f,0x3832b927,
0xb3653a99,0x3bc93887,0x36aab996,0xbb46b9ba,0xb7b7bbed,0xbb02304e,0x34d53bfc,0x3ba02bd9,0x3b913927,0x3534ba1f,0xbae9ba3f,0xb8073900,0xbb5a28b6,0x364e3bff,0x3bd43115,0xb2a1bbe6,
0xb1153ab5,0x3be6385d,0xa8b6bb6e,0xbbffb5f1,0xb900bbbc,0xba3f3414,0x3a1f3b30,0x3927b705,0x3bfc375e,0x2bd9bb1a,0xbbedb475,0x304e3baf,0xb9ba3593,0x39963b80,0x3887b832,0xba99bad0,
0xad7e3ad0,0x3bf83832,0xb7b7bbff,0xbb0228b6,0xb9febb6e,0xb94d35f1,0x3bed3887,0x304eba99,0x3bd43414,0xb2a1bbbc,0xb9963534,0x39ba3b91,0xb6aa3900,0x3b463a3f,0xb115bba0,0xbbe6b4d5,
0xa2483ae9,0x3c003807,0xba99bb30,0xb8873705,0xbad0bb02,0xb83237b7,0x3b462d7e,0xb6aabbf8,0x3b1a28b6,0xb75ebbff,0xaf0e3a7c,0x3bf438b0,0xabd93ab5,0x3bfc385d,0xba5ebb5a,0xb8d8364e,
0x2bd93b02,0x3bfc37b7,0xbbedb927,0xb04e3a1f,0xbb6eba7c,0xb5f138b0,0x385db6aa,0xbab5bb46,0x39dcb1db,0xb972bbdd,0x38323c00,0x3ad02248,0x34d53bbc,0x3ba03414,0xbbf4b705,0x2f0e3b30,
0x304e3b1a,0x3bed375e,0xbb91b475,0x35343baf,0xbbd4b9dc,0xb2a13972,0x2248ba7c,0xbc00b8b0,0x3832b64e,0xbad0bb5a,0x3b803a99,0x3593b887,0x39003bfc,0x3a3fabd9,0xb9273414,0x3a1f3bbc,
0x32a13b30,0x3bd43705,0xb996304e,0x39ba3bed,0xbbffb927,0xa8b63a1f,0xb832bbf4,0xbad0af0e,0x3475b8b0,0xbbafba7c,0x3ba03593,0xb4d5bb80,0x3ae93b6e,0x3807b5f1,0x2bd93a99,0x3bfc3887,
0x34753b46,0x3baf36aa,0xb4d53832,0x3ba03ad0,0xbbedb85d,0x304e3ab5,0xbb30bb5a,0xb705364e,0x2248b9fe,0xbc00b94d,0x3887b414,0xba99bbbc,0x3be63a1f,0x3115b927,0x39dc3bf4,0x3972af0e,
0x35933b5a,0x3b80364e,0x31153a99,0x3be63887,0xbba0b705,0x34d53b30,0xbbf4b8d8,0x2f0e3a5e,0xb414bb02,0xbbbcb7b7,0xabd9ba1f,0xbbfcb927,0x3bd43832,0xb2a1bad0,0x3c003972,0xa248b9dc,
0x36aa3b6e,0x3b4635f1,0x38b03bdd,0x3a7c31db,0xbb1ab534,0x375e3b91,0xba3fb04e,0x39003bed,0xb807bbaf,0xbae9b475,0xb94dbbf8,0xb9fead7e,0x3ab53365,0xb85dbbc9,0x39ba28b6,0xb996bbff,
0x37b73b80,0x3b023593,0x3b1a3bc9,0x375eb365,0xba5eb2a1,0x38d83bd4,0xb53435f1,0x3b913b6e,0xb9babbfc,0xb996abd9,0xbbddbae9,0xb1db3807,0x38b0ad7e,0xba7cbbf8,0x28b6b900,0xbbffba3f,
0x385d3b91,0x3ab53534,0x3c003a5e,0x2248b8d8,0xb972ad7e,0x39dc3bf8,0x33653a3f,0x3bc93900,0xbb02bbe6,0xb7b73115,0xbb1ab6aa,0x375e3b46,0x3414b64e,0xbbbcbb5a,0xb94dbbdd,0xb9feb1db,
0x38d83ba0,0x3a5e34d5,0x3b3037b7,0xb705bb02,0xb85d28b6,0x3ab53bff,0x39ba3be6,0x39963115,0xbbc9bb6e,0xb36535f1,0xb6aa31db,0x3b463bdd,0xaf0eb94d,0xbbf4b9fe,0xbbf8bae9,0xad7e3807,
0x394d3baf,0x39fe3475,0x38d82d7e,0xba5ebbf8,0xb64e3115,0x3b5a3be6,0x3bd43b80,0x32a1b593,0xbbffba99,0x28b63887,0x336539ba,0x3bc93996,0xb75ebae9,0xbb1ab807,0xba3fb534,0x39003b91,
0x39ba3bbc,0x39963414,0x31dbb534,0xbbddbb91,0xb3653475,0x3bc93baf,0x3b803927,0xb593ba1f,0xbba0b972,0x34d539dc,0x3a3f3be6,0x39003115,0xb9febbd4,0xb94db2a1,0xb04e35f1,0x3bed3b6e,
0x3a1f3bc9,0x39273365,0xb475b972,0xbbafb9dc,0xabd9364e,0x3bfc3b5a,0x38d831db,0xba5ebbdd,0xbab5b807,0x385d3ae9,0x3c003b30,0x2248b705,0xbb80bbf4,0xb5932f0e,0x38b03b1a,0x3a7c375e,
0x3a7c3bd4,0x38b032a1,0xb972bb5a,0xb9dcb64e,0x2f0e3807,0x3bf43ae9,0x2d7eb534,0xbbf8bb91,0xb94db4d5,0x39fe3ba0,0x3a5e37b7,0xb8d8bb02,0xbc00bb46,0x224836aa,0x3bdd3bc9,0x31dbb365,
0x3ad03bdd,0x383231db,0xbb80bc00,0xb5932248,0x347538d8,0x3baf3a5e,0xb75eb9fe,0xbb1ab94d,0xb705ad7e,0x3b303bf8,0x3414af0e,0xbbbcbbf4,0xbb6eb9dc,0x35f13972,0x3ab538b0,0xb85dba7c,
0x3b1a3be6,0x375e3115,0xbbf4bb46,0x2f0e36aa,0x37053996,0x3b3039ba,0xbae9bbd4,0xb807b2a1,0xb1db304e,0x3bdd3bed,0xb64eb94d,0xbb5ab9fe,0xb9dcb7b7,0x39723b02,0x3365ad7e,0xbbc9bbf8,
0x3b5a3bed,0x364e304e,0xbab5b94d,0x385d39fe,0x38b03a3f,0x3a7c3900,0xbbffbba0,0x28b634d5,0x2d7e3593,0x3bf83b80,0xbb02bbc9,0xb7b7b365,0xb705b1db,0x3b303bdd,0xb807b9ba,0xbae9b996,
0x3b913bf4,0x35342f0e,0xb807b4d5,0x3ae93ba0,0x39ba3ad0,0x39963832,0xba99b972,0x388739dc,0x3593385d,0x3b803ab5,0xbbe6bb6e,0x311535f1,0xad7e304e,0x3bf83bed,0xbbafbbfc,0xb475abd9,
0x3bbc3bf8,0x34142d7e,0xabd92f0e,0x3bfc3bf4,0x3a993b46,0x388736aa,0xb64eb365,0x3b5a3bc9,0x38b039ba,0x3a7c3996,0xb972b85d,0x39dc3ab5,0x34753705,0x3baf3b30,0xbb1aba5e,0x375e38d8,
0x3bdd3bfc,0x31db2bd9,0x364e3807,0x3b5a3ae9,0x3b463ba0,0x36aa34d5,0x31153475,0x3be63baf,0x3a3f3ad0,0x39003832,0xad7e28b6,0x3bf83bff,0x38d83996,0x3a5e39ba,0xb534b2a1,0x3b913bd4,
0x3bf43bff,0x2f0e28b6,0x3a1f3a7c,0x392738b0,0x3bbc3bdd,0x341431db,0x394d39ba,0x39fe3996,0x3b5a3b91,0x364e3534,0x385d38d8,0x3ab53a5e,0x3ad03b1a,0x3832375e,0x36aa37b7,0x3b463b02,
0x3bff3c00,0x28b62248,0x3bc93bd4,0x336532a1,0x3bf83bfc,0x2d7e2bd9,0x3baf3bbc,0x34753414,0x3bed3bf4,0x304e2f0e,0x3b913ba0,0x353434d5,0x3bdd3be6,0x31db3115,0x3b6e3b80,0x35f13593,
0xb5933b6e,0x3b8035f1,0xb1153bdd,0x3be631db,0x34d5bb91,0xbba0b534,0x2f0ebbed,0xbbf4b04e,0xb4143baf,0x3bbc3475,0xabd93bf8,0x3bfc2d7e,0x32a1bbc9,0xbbd4b365,0x2248bbff,0xbc00a8b6,
0x37b73b46,0x3b02b6aa,0x3b1a3832,0x375ebad0,0xb8d8bab5,0xba5e385d,0xbb91b64e,0xb5343b5a,0x39ba39fe,0x3996b94d,0x3bdd3414,0x31dbbbbc,0xba7cb927,0xb8b03a1f,0xbbffaf0e,0xa8b63bf4,
0x3bd43534,0x32a1bb91,0x39bab8d8,0xb996ba5e,0xbbffad7e,0x28b63bf8,0xb8323a3f,0x3ad03900,0x3bafb115,0xb475bbe6,0x34d5bb46,0xbba0b6aa,0xbae9364e,0x38073b5a,0xabd93bdd,0x3bfc31db,
0x3a5eb75e,0xb8d8bb1a,0xb705bbaf,0xbb303475,0xb85d39dc,0x3ab53972,0x39ba3a7c,0x3996b8b0,0x3365bb5a,0xbbc9b64e,0xbb46b887,0xb6aa3a99,0x2f0e3bfc,0x3bf42bd9,0x3bf83414,0x2d7ebbbc,
0x2bd9bbaf,0xbbfcb475,0xbbedad7e,0x304e3bf8,0x35f13be6,0x3b6eb115,0x3ab5b593,0xb85dbb80,0xb9dcba99,0xb9723887,0xb83239ba,0x3ad03996,0x3ba03807,0x34d5bae9,0x2f0ebb91,0xbbf4b534,
0xb9babae9,0xb9963807,0xb1db3b30,0x3bdd3705,0x3bc937b7,0x3365bb02,0xb593bbf8,0xbb802d7e,0xbba028b6,0x34d53bff,0x3a3f3a7c,0x3900b8b0,0x394db85d,0xb9febab5,0xbbedb64e,0xb04e3b5a,
0xbbf8b365,0x2d7e3bc9,0x3b0239dc,0x37b7b972,0x39feb64e,0xb94dbb5a,0xbbedb1db,0x304e3bdd,0xb2a13ae9,0x3bd43807,0x39bab705,0xb996bb30,0xb6aabbf4,0xbb462f0e,0xb1153b1a,0x3be6375e,
0xb8b0385d,0x3a7c3ab5,0x39dcb5f1,0xb972bb6e,0xaf0ebbbc,0xbbf4b414,0xad7e3b30,0x3bf83705,0x39fe3b1a,0x394db75e,0xb8d8bbaf,0xba5e3475,0xbc00b593,0x22483b80,0x3bdd3832,0x31dbbad0,
0x33653bdd,0x3bc931db,0xb6aabc00,0xbb462248,0xbb02ba5e,0xb7b738d8,0x3ba0394d,0x34d5b9fe,0x3b912d7e,0xb534bbf8,0xbae92f0e,0x38073bf4,0xb64e3972,0x3b5a39dc,0x32a1ba7c,0xbbd4b8b0,
0x3b1a3a7c,0x375eb8b0,0xbbf4b593,0x2f0e3b80,0xbb30a248,0x37053c00,0x3807b85d,0xbae9bab5,0x31dbba5e,0xbbddb8d8,0x364e3bfc,0x3b5a2bd9,0x39723baf,0x39dcb475,0xbbc9b927,0xb3653a1f,
0x3b6e304e,0xb5f1bbed,0xb2a139fe,0x3bd4394d,0xb1153a3f,0x3be63900,0xb9dcbba0,0xb97234d5,0xba1fbb80,0xb9273593,0x3baf3365,0xb475bbc9,0x3b9131db,0xb534bbdd,0xb41439ba,0x3bbc3996,
0x3534b900,0xbb91ba3f,0x3ae93b1a,0x3807b75e,0x39ba3bc9,0x3996b365,0xba9928b6,0x38873bff,0xbb80b2a1,0x35933bd4,0xb115bb5a,0xbbe6b64e,0x2d7eba5e,0xbbf8b8d8,0x3baf39fe,0x3475b94d,
0xb807bbf8,0xbae9ad7e,0x39feaf0e,0xb94dbbf4,0x3bdd36aa,0xb1dbbb46,0x35f13bc9,0x3b6e3365,0xb11539ba,0x3be63996,0xbbffb85d,0x28b63ab5,0xbb02bb30,0xb7b73705,0x34d5b8d8,0xbba0ba5e,
0xbbddb9fe,0xb1db394d,0xb64ebbbc,0xbb5ab414,0x36aab75e,0xbb46bb1a,0x3be637b7,0xb115bb02,0x3a3f3bc9,0x3900b365,0xad7e39dc,0x3bf83972,0xba5ea248,0x38d83c00,0xbb91bab5,0xb534385d,
0xba3fa8b6,0x39003bff,0xbbf8b8b0,0x2d7e3a7c,0xb807bbdd,0xbae9b1db,0x2bd9b9ba,0xbbfcb996,0x3b6e3534,0xb5f1bb91,0x3bd43a5e,0x32a1b8d8,0x33653b1a,0x3bc9375e,0xb59337b7,0x3b803b02,
0xa8b63996,0x3bff39ba,0xb365385d,0x3bc93ab5,0xbbf8b9fe,0xad7e394d,0xbbafbae9,0xb4753807,0x304eb900,0xbbedba3f,0x3534b75e,0xbb91bb1a,0x3bdd3a7c,0x31dbb8b0,0x3b6e3b46,0x35f1b6aa,
0x39dc3c00,0x3972a248,0x3ad03bd4,0x3832b2a1,0xb9272bd9,0x3a1f3bfc,0xb7b73414,0x3b023bbc,0xba5ebbf4,0xb8d82f0e,0xbb30bba0,0xb70534d5,0x3887b115,0xba99bbe6,0x364eb593,0xbb5abb80,
0x3bf43972,0xaf0eb9dc,0x3a1f3115,0xb927bbe6,0x34143a99,0x3bbc3887,0x39fe3c00,0x394d2248,0xbb5ab705,0x364e3b30,0xb85d304e,0x3ab53bed,0xb832bba0,0xbad0b4d5,0xbb46bbaf,0xb6aa3475,
0x3887abd9,0xba99bbfc,0xb5f1bae9,0xbb6eb807,0x3b803ba0,0x3593b4d5,0x3a7c3475,0xb8b0bbaf,0xaf0e3832,0x3bf43ad0,0x3a1f3bff,0x392728b6,0xbbedb996,0x304e39ba,0xb70532a1,0x3b303bd4,
0xb414ba1f,0xbbbcb927,0xbbfcba3f,0x2bd93900,0x3a993593,0xb887bb80,0xb64ebad0,0xbb5ab832,0x3a7c3c00,0x38b02248,0x39dc32a1,0xb972bbd4,0xb4753534,0x3baf3b91,0x3b1a3bed,0x375eb04e,
0xbb30bbf4,0xb7052f0e,0xb41434d5,0x3bbc3ba0,0x2248b832,0xbc00bad0,0xbbddb9dc,0x31db3972,0x3b46385d,0xb6aabab5,0xb8b0bb6e,0xba7cb5f1,0x3a1f3bed,0x3927304e,0x37b7abd9,0xbb02bbfc,
0xbb5ab8d8,0x364e3a5e,0x3ab53bfc,0x385d2bd9,0xba7cbbf4,0xb8b0af0e,0xa8b6375e,0x3bff3b1a,0x2d7eb6aa,0xbbf8bb46,0xbb02b832,0x37b73ad0,0x3b303887,0xb705ba99,0xbae9bc00,0xb807a248,
0xb4d53115,0x3ba03be6,0x3a3f36aa,0xb900bb46,0xbb91b996,0x353439ba,0x3bbc3bd4,0x3414b2a1,0xba99bbed,0xb887b04e,0x35f139fe,0x3b6e394d,0xa8b6b7b7,0xbbffbb02,0xb832ad7e,0x3ad03bf8,
0x38323a99,0x3ad03887,0xb593b996,0xbb80b9ba,0xb475304e,0x3baf3bed,0x375e2bd9,0xbb1abbfc,0xbb30b927,0x37053a1f,0x3bbc3a3f,0xb414b900,0xbb6ebbff,0xb5f128b6,0x3ab53be6,0x385d3115,
0x3be63bd4,0x3115b2a1,0xbbffbb5a,0x28b6364e,0x39003ae9,0x3a3f3807,0xba1fbb91,0xb927b534,0xabd934d5,0x3bfc3ba0,0xb04eb7b7,0xbbedbb02,0xb9bab6aa,0x39963b46,0x38873365,0xba99bbc9,
0x3a1f3832,0xb927bad0,0xb47528b6,0x3baf3bff,0x3bfc3b6e,0xabd9b5f1,0xba5eb887,0x38d83a99,0x3ab53bbc,0x385d3414,0xbc00bb91,0x22483534,0x35933900,0x3b803a3f,0xba7cbba0,0xb8b0b4d5,
0x2248b414,0xbc00bbbc,0x3a993b91,0x38873534,0x38323475,0xbad0bbaf,0x36aa3927,0x3b463a1f,0x3b1a39dc,0xb75eb972,0xaf0e3115,0x3bf43be6,0x3bfc3bd4,0x2bd9b2a1,0xb8d8b5f1,0x3a5e3b6e,
0xb9febb02,0xb94db7b7,0x3a5e3927,0xb8d8ba1f,0xb64eb8b0,0xbb5aba7c,0x3bd43b46,0xb2a1b6aa,0x28b6b1db,0xbbffbbdd,0x3bc93c00,0x33652248,0x375e3414,0xbb1abbbc,0x3a3f3b30,0x39003705,
0xbbedbba0,0x304e34d5,0xb534b7b7,0xbb91bb02,0xbbd4bbff,0xb2a1a8b6,0x2248b115,0xbc00bbe6,0xbad0bb6e,0xb832b5f1,0x359331db,0xbb80bbdd,0xb900b9fe,0xba3fb94d,0x39273807,0xba1fbae9,
0xb85db705,0x3ab53b30,0xbc00bbed,0x2248304e,0xb9dcb927,0x39723a1f,0xbbc9bbf4,0xb365af0e,0xbb02ba7c,0x37b738b0,0xbb1abb80,0xb75eb593,0xbbbcbb6e,0x341435f1,0xb9feba99,0xb94db887,
0x34753593,0x3baf3b80,0xb4d5b365,0x3ba03bc9,0x304e32a1,0x3bed3bd4,0xb705b5f1,0x3b303b6e,0xa2482bd9,0x3c003bfc,0xb887b807,0x3a993ae9,0xb115ad7e,0x3be63bf8,0xb972b900,0x39dc3a3f,
0x3b463b5a,0x36aa364e,0x3a7c3a99,0x38b03887,0x3b1a3b30,0x375e3705,0x3a3f3a5e,0x390038d8,0x3ae93b02,0x380737b7,0x39fe3a1f,0x394d3927,0x3ab53ad0,0x385d3832,0x39ba39dc,0x39963972,
0x28b63c00,0x3bffa248,0x33653bd4,0x3bc9b2a1,0xad7ebbfc,0xbbf82bd9,0xb475bbbc,0xbbaf3414,0x304e3bf4,0x3bedaf0e,0x35343ba0,0x3b91b4d5,0xb1dbbbe6,0xbbdd3115,0xb5f1bb80,0xbb6e3593,
0x3bf4a8b6,0xaf0ebbff,0x3a1fb8b0,0xb927ba7c,0xbbbc31db,0x34143bdd,0xb94d3996,0x39fe39ba,0x3b5ab534,0xb64ebb91,0x385dba5e,0xbab5b8d8,0xbad0375e,0x38323b1a,0xb6aa3b02,0x3b4637b7,
0xb1dbbbfc,0xbbdd2bd9,0xbb5ab807,0xb64e3ae9,0x36aa3ba0,0x3b46b4d5,0x3be63475,0x3115bbaf,0xb900bad0,0xba3f3832,0xbbf8a8b6,0x2d7e3bff,0x3a5e3996,0x38d8b9ba,0x3b91b2a1,0xb534bbd4,
0xbbbc2d7e,0x34143bf8,0x2bd93bf4,0x3bfc2f0e,0x3a99b6aa,0xb887bb46,0xb64ebbc9,0xbb5a3365,0xb8b03996,0x3a7c39ba,0x39723ab5,0x39dcb85d,0x3475bb30,0xbbafb705,0xbb1ab8d8,0xb75e3a5e,
0x35343bf4,0x3b91af0e,0x3ae9b4d5,0xb807bba0,0xb996bad0,0xb9ba3832,0xb8873972,0x3a9939dc,0x3b80385d,0x3593bab5,0x3115bb6e,0xbbe6b5f1,0xbbf8b04e,0x2d7e3bed,0x34753bfc,0x3bafabd9,
0x3b5ab04e,0xb64ebbed,0xbab5b9fe,0xb85d394d,0xb8b03900,0x3a7c3a3f,0x3bff34d5,0x28b6bba0,0x2d7ebb80,0xbbf8b593,0xbb023365,0x37b73bc9,0x37053bdd,0x3b30b1db,0x3807b996,0xbae9b9ba,
0xb75ebbe6,0xbb1a3115,0xaf0e3b46,0x3bf436aa,0x3b303996,0x3705b9ba,0xb807bbd4,0xbae932a1,0xbbddb04e,0x31db3bed,0x3b5a394d,0x364eb9fe,0x3972b7b7,0xb9dcbb02,0xbbc9ad7e,0x33653bf8,
0xbad031db,0x38323bdd,0x3b802248,0xb593bc00,0x3475ba5e,0xbbafb8d8,0xb75e394d,0x3b1a39fe,0x37053bf8,0x3b30ad7e,0xb414bbf4,0xbbbcaf0e,0xbb6eb972,0xb5f139dc,0x3ab53a7c,0x385db8b0,
0x38b03bd4,0x3a7cb2a1,0xb9dcbb5a,0xb972364e,0xbbf4b807,0xaf0e3ae9,0x3bf83534,0xad7ebb91,0x39feb4d5,0xb94dbba0,0xb8d837b7,0x3a5e3b02,0xa2483b46,0x3c0036aa,0xb1dbbbc9,0xbbddb365,
0x3a1fb365,0xb927bbc9,0xb47539dc,0x3baf3972,0x2bd93b5a,0x3bfc364e,0xb8d8bbdd,0xba5e31db,0xbab5bae9,0xb85d3807,0x3c003705,0xa248bb30,0x3b802f0e,0xb593bbf4,0xb8b0375e,0x3a7c3b1a,
0xb996bbbc,0xb9ba3414,0x3bdd3534,0xb1dbbb91,0x3bc93475,0xb365bbaf,0xb5933927,0x3b803a1f,0xb4d53972,0x3ba039dc,0xb900bbe6,0xba3f3115,0xb94dbbd4,0xb9fe32a1,0x3bed35f1,0xb04ebb6e,
0xb94d3475,0x39fe3baf,0xb8d8bbf8,0xba5e2d7e,0xb64ebbe6,0xbb5ab115,0x3bd43593,0xb2a1bb80,0x3bff3887,0x28b6ba99,0xb3653996,0x3bc939ba,0xb75e3807,0x3b1a3ae9,0xba3fbb91,0xb9003534,
0x3a5e3ba0,0x38d8b4d5,0xb70537b7,0x3b303b02,0xbab5a8b6,0x385d3bff,0xb996bbe6,0xb9ba3115,0xb365bb6e,0xbbc9b5f1,0x3b4631db,0xb6aabbdd,0x3bf4394d,0x2f0eb9fe,0x2d7e3ae9,0x3bf83807,
0x385db534,0xbab5bb91,0x3c0038d8,0xa248ba5e,0x39723bf8,0x39dcad7e,0xb3653900,0x3bc93a3f,0xbb02b115,0x37b73be6,0xbb1abb46,0xb75e36aa,0xb414bb5a,0xbbbcb64e,0x394db1db,0xb9febbdd,
0xbb02bb80,0xb7b73593,0xb75ebbc9,0xbb1ab365,0x38d8b2a1,0xba5ebbd4,0x3b9135f1,0xb534bb6e,0x39963bfc,0x39baabd9,0x31db3ae9,0x3bdd3807,0xba7cad7e,0x38b03bf8,0xbbffb900,0x28b63a3f,
0xb6aa35f1,0x3b463b6e,0xb8b031db,0x3a7c3bdd,0xbb1abb91,0xb75e3534,0xba3fbbed,0xb900304e,0x3807b475,0xbae9bbaf,0x394dad7e,0xb9febbf8,0x3ab53bc9,0x385db365,0x39ba3bff,0x3996a8b6,
0x3b803b5a,0x3593b64e,0x3be63a99,0x3115b887,0xb4d53705,0x3ba03b30,0xaf0e38d8,0x3bf43a5e,0xbbbcbb02,0xb41437b7,0xbbfcba1f,0xabd93927,0x32a1b832,0xbbd4bad0,0x2248b972,0xbc00b9dc,
0x3475b6aa,0xbbafbb46,0xb4d5bad0,0xbba0b832,0x3bed3ab5,0x304eb85d,0x3b30364e,0xb705bb5a,0x2248394d,0x3c0039fe,0x38873bbc,0x3a993414,0xbbe6b927,0x31153a1f,0xb9dcaf0e,0x39723bf4,
0xbbd4bb30,0xb2a13705,0xb9bab04e,0x39963bed,0xa8b6b927,0xbbffba1f,0xbad0bbf4,0xb8322f0e,0x3baf38b0,0xb475ba7c,0x34d5b593,0xbba0bb80,0x38073b6e,0x3ae935f1,0x3bfc3a99,0x2bd9b887,
0xb04e375e,0x3bed3b1a,0x3b913baf,0x3534b475,0xbbd4b972,0x32a139dc,0x224838b0,0x3c003a7c,0xb832bb5a,0xbad0b64e,0xbb80b887,0x35933a99,0x39002bd9,0xba3fbbfc,0xb927bbbc,0xba1fb414,
0x3bfc3b02,0x2bd9b7b7,0xb04eb927,0xbbedba1f,0x35f13a7c,0x3b6e38b0,0x3ab536aa,0xb85dbb46,0xb972b1db,0x39dc3bdd,0x3ad03c00,0x3832a248,0xbba0bbbc,0xb4d53414,0xaf0e3705,0x3bf43b30,
0xa248b807,0xbc00bae9,0xba99b705,0x38873b30,0x3ad037b7,0xb832bb02,0xbb46bbf8,0xb6aa2d7e,0x3b1a3bff,0x375ea8b6,0xaf0eb8b0,0xbbf4ba7c,0x2bd9385d,0x3bfc3ab5,0x3a5e364e,0xb8d8bb5a,
0xbbf8bad0,0x2d7e3832,0x3b023bff,0x37b728b6,0xb94dbb6e,0xb9feb5f1,0x304e3887,0x3bed3a99,0x32a1b414,0xbbd4bbbc,0xb9bab534,0x39963b91,0x3b463900,0xb6aaba3f,0xbbe6bba0,0xb11534d5,
0x3115385d,0x3be63ab5,0x28b6b5f1,0xbbffbb6e,0xb900b414,0x3a3f3bbc,0x3a1f3705,0xb927bb30,0xbbfcbb1a,0x2bd9375e,0x3bed3baf,0x304eb475,0xb9babb80,0xb996b593,0x38873ad0,0x3a993832,
0x3bc93a99,0xb365b887,0xbb46b996,0x36aa39ba,0x3b023bed,0x37b7304e,0xbba0bbfc,0xb4d52bd9,0x35343927,0x3b913a1f,0xb807ba3f,0xbae9b900,0xb64ea8b6,0x3b5a3bff,0x32a1b115,0xbbd4bbe6,
0xb4d5b8b0,0xbba0ba7c,0x3a3f3b80,0x39003593,0x35342248,0xbb91bc00,0x3414385d,0x3bbc3ab5,0x3a9938d8,0xb887ba5e,0xb5f1abd9,0x3b6e3bfc,0x3bff3baf,0x28b6b475,0xbad0b927,0x38323a1f,
0xbb6eba5e,0x35f138d8,0x32a1abd9,0xbbd4bbfc,0xbbe6bbf4,0xb1152f0e,0x3972375e,0xb9dcbb1a,0xba1fbb46,0xb927b6aa,0x3baf3ad0,0xb475b832,0xb534b887,0xbb91ba99,0x3bbc3c00,0x3414a248,
0x37053900,0x3b303a3f,0xbbbcbb1a,0x3414375e,0x22483365,0x3c003bc9,0xbbddbbff,0xb1db28b6,0xb6aab2a1,0x3b463bd4,0xba7cbb5a,0xb8b0b64e,0xba1fb8d8,0x39273a5e,0xb7b7b94d,0xbb02b9fe,
0x3ae93a1f,0xb807b927,0x394d3a3f,0x39fe3900,0x3bdd3b80,0xb1dbb593,0x35f13832,0x3b6e3ad0,0x3be63c00,0x3115a248,0x28b632a1,0x3bff3bd4,0x3b023b91,0x37b73534,0xb4d5b04e,0x3ba03bed,
0xb887b94d,0xba99b9fe,0x35f13414,0xbb6ebbbc,0xb593b75e,0xbb80bb1a,0x38b037b7,0xba7cbb02,0xaf0eb365,0xbbf4bbc9,0x3a1f3972,0xb927b9dc,0x304e2248,0xbbedbc00,0x3b303ab5,0xb705b85d,
0xba3fb9dc,0x39003972,0xbbf8bbe6,0x2d7e3115,0xbae9ba99,0x38073887,0xbbfcbc00,0xabd92248,0xbb6ebb30,0x35f13705,0xbbd4bbed,0xb2a1b04e,0xbbc9bba0,0x336534d5,0xbb80bbaf,0xb593b475,
0x39723996,0x39dc39ba,0x3832385d,0x3ad03ab5,0x3927394d,0x3a1f39fe,0x37b73807,0x3b023ae9,0x38d83900,0x3a5e3a3f,0x3705375e,0x3b303b1a,0x388738b0,0x3a993a7c,0x364e36aa,0x3b5a3b46,
0x36aa3b5a,0x3b46b64e,0x38b03a99,0x3a7cb887,0xb75ebb30,0xbb1a3705,0xb900ba5e,0xba3f38d8,0x38073b02,0x3ae9b7b7,0x394d3a1f,0x39feb927,0xb85dbad0,0xbab53832,0xb996b9dc,0xb9ba3972,
0x3475bb80,0xbbafb593,0xb4d5bbc9,0xbba03365,0xb04e3bd4,0x3bed32a1,0x37053b6e,0x3b30b5f1,0xa248bbfc,0xbc00abd9,0xb887bae9,0xba993807,0x31153bf8,0x3be6ad7e,0x39723a3f,0x39dcb900,
0xbab53705,0x385d3b30,0xa2483bed,0x3c00304e,0x3972b927,0xb9dcba1f,0xb365bbf4,0xbbc92f0e,0xb7b73a7c,0x3b0238b0,0x375e3b80,0x3b1ab593,0x3414bb6e,0xbbbcb5f1,0xb94dba99,0xb9fe3887,
0x3bed34d5,0x304ebba0,0x3534bb02,0xbb91b7b7,0xbbd428b6,0x32a13bff,0x22483be6,0x3c003115,0x3ad0b5f1,0xb832bb6e,0xb593bbdd,0xbb8031db,0xb900394d,0x3a3f39fe,0x39273ae9,0x3a1fb807,
0xb94dbb02,0xb9fe37b7,0xb8d83927,0x3a5e3a1f,0x3b5a38b0,0x364eba7c,0x32a1bb46,0xbbd4b6aa,0xbbffb1db,0x28b63bdd,0x33653c00,0x3bc9a248,0x3b1ab414,0xb75ebbbc,0xb900bb30,0xba3f3705,
0x22483bbc,0x3c003414,0x3a99b534,0xb887bb91,0xb832bbaf,0xbad03475,0xb6aa3a1f,0x3b463927,0x3b1a3972,0x375eb9dc,0xaf0ebbe6,0xbbf4b115,0xbbfcb2a1,0x2bd93bd4,0x38d83b6e,0x3a5eb5f1,
0x3927b832,0xba1fbad0,0xbbafa8b6,0x34753bff,0xabd93b6e,0x3bfc35f1,0x38d8b887,0xba5eba99,0xb85dbbbc,0xbab53414,0xa2483b91,0x3c003534,0x3b803900,0x3593ba3f,0xb8b0bba0,0xba7c34d5,
0xbbe6b2a1,0x31153bd4,0x3bff364e,0x28b6bb5a,0x3900b807,0xba3fbae9,0xba1f3534,0x39273b91,0x2bd93ba0,0x3bfc34d5,0x304ebb02,0xbbedb7b7,0xb9babb46,0xb99636aa,0x38873bc9,0x3a99b365,
0x3ad03a99,0x3832b887,0xbb80b996,0xb59339ba,0xbbafb04e,0x34753bed,0x3b1aabd9,0xb75ebbfc,0x3705b927,0xbb30ba1f,0xb4143a3f,0x3bbc3900,0x35f13bff,0x3b6e28b6,0xb85dbbe6,0xbab53115,
0xb4d5bbe6,0xbba0b115,0x3a3f3b46,0x3900b6aa,0x3b9139ba,0x3534b996,0xbbbcb2a1,0x34143bd4,0xba99304e,0x38873bed,0x35f1b94d,0xbb6eb9fe,0x28b6bb02,0xbbffb7b7,0x38323bf8,0x3ad0ad7e,
0xb64e38d8,0x3b5a3a5e,0xb85dbbfc,0xbab52bd9,0xb8b0bbf4,0xba7c2f0e,0x3bff375e,0xa8b6bb1a,0x3bf836aa,0xad7ebb46,0xb7b73832,0x3b023ad0,0xb7053887,0x3b303a99,0xb807bc00,0xbae92248,
0x3b302f0e,0xb705bbf4,0x34143ba0,0x3bbc34d5,0x22483ad0,0x3c003832,0xbbddb972,0xb1db39dc,0xbb46bab5,0xb6aa385d,0x38b0b5f1,0xba7cbb6e,0x3a1fb04e,0xb927bbed,0x37b73bfc,0x3b022bd9,
0xbbbcba1f,0xb4143927,0x2bd9ba3f,0xbbfcb900,0x3887b593,0xba99bb80,0x3b5a3ad0,0x364eb832,0x38b03c00,0x3a7ca248,0xb97232a1,0x39dc3bd4,0xbbafb534,0x34753b91,0xb75ebbed,0xbb1ab04e,
0x38873bfc,0x3a992bd9,0xb5f13807,0x3b6e3ae9,0xbb80b4d5,0x35933ba0,0xba7cbbaf,0xb8b03475,0xaf0ebad0,0xbbf4b832,0x3a1fa8b6,0xb927bbff,0x3bed39ba,0x304eb996,0x37053bd4,0x3b3032a1,
0x2f0eb972,0xbbf4b9dc,0x3927b115,0xba1fbbe6,0x3bbc3a99,0x3414b887,0x394d3c00,0x39fea248,0xb64e3705,0x3b5a3b30,0xbab5b04e,0x385d3bed,0xbad0bba0,0xb83234d5,0xb6aabbaf,0xbb46b475,
0xb9dca248,0x39723c00,0xbad0b2a1,0x38323bd4,0xb927bbfc,0xba1fabd9,0xb7b7bbbc,0xbb02b414,0x3a5e2f0e,0xb8d8bbf4,0x3b3034d5,0xb705bba0,0x38873be6,0x3a993115,0x364e3b80,0x3b5a3593,
0x3bff3996,0xa8b6b9ba,0x3bc9385d,0xb365bab5,0x2d7e39fe,0x3bf8394d,0x34753ae9,0x3baf3807,0xbbedb900,0x304e3a3f,0xbb91b75e,0x35343b1a,0xb1dbba7c,0xbbddb8b0,0xb5f1bb46,0xbb6eb6aa,
0xba3fbbff,0xb90028b6,0xbbf8ba7c,0xad7e38b0,0x3807b1db,0xbae9bbdd,0xabd9b996,0xbbfcb9ba,0x3b6e3b91,0x35f1b534,0x3bd438d8,0xb2a1ba5e,0xb365375e,0x3bc93b1a,0x35933b02,0x3b8037b7,
0x31db39fe,0x3bdd394d,0x3b5a3bbc,0x364eb414,0xbb46b75e,0x36aa3b1a,0xb11537b7,0x3be63b02,0xb900bbc9,0xba3fb365,0xbbf8b9dc,0x2d7e3972,0x38d8a248,0xba5ebc00,0xb534bab5,0xbb91b85d,
0x3807ad7e,0xbae9bbf8,0xb9febbf4,0xb94daf0e,0x3bdd3b46,0x31dbb6aa,0x35f1b365,0xbb6ebbc9,0x31153996,0x3be639ba,0x3bff3ab5,0x28b6b85d,0xbb02b705,0x37b73b30,0x34d53a5e,0x3ba038d8,
0xbb91b900,0x35343a3f,0x38073b1a,0x3ae9375e,0xb996bbc9,0xb9bab365,0xb887a8b6,0x3a993bff,0x3593b2a1,0xbb80bbd4,0xbbe6bb5a,0xb115364e,0x3bf83a5e,0xad7eb8d8,0xb475b9fe,0xbbafb94d,
0x3b6e3bed,0x35f1b04e,0xb2a1b94d,0xbbd4b9fe,0x31153900,0x3be63a3f,0x39dc34d5,0xb972bba0,0xba1fb593,0x39273b80,0x3baf3bc9,0x3475b365,0xbb91bbdd,0xb53431db,0x34143996,0x3bbc39ba,
0xb75eba7c,0xbb1ab8b0,0xaf0e3593,0x3bf43b80,0x3705a248,0xbb30bc00,0xbae9b85d,0x38073ab5,0x3bdd3a5e,0xb1dbb8d8,0xbb5abbfc,0xb64e2bd9,0x39dc3baf,0x39723475,0xb365b927,0xbbc9ba1f,
0xb36531db,0x3bc93bdd,0x36aa2248,0xbb46bc00,0xbb02b8d8,0x37b73a5e,0x3ba039fe,0xb4d5b94d,0xbb91bbf8,0xb5342d7e,0x3ae93bf4,0x38072f0e,0xb64eb9dc,0xbb5ab972,0x32a138b0,0x3bd43a7c,
0x3a7c385d,0xb8b0bab5,0xb972b5f1,0x39dc3b6e,0x3bf43bbc,0x2f0eb414,0xbbf8bb30,0x2d7e3705,0x394d3b1a,0x39fe375e,0xba5ebbaf,0xb8d8b475,0xa2483593,0x3c003b80,0xb1dbb832,0xbbddbad0,
0xbbf8bbc9,0xad7e3365,0x3b023972,0xb7b7b9dc,0xb9febb5a,0xb94db64e,0x3bed3bdd,0x304eb1db,0xb2a1b807,0xbbd4bae9,0x39ba3b30,0x39963705,0x36aa2f0e,0xbb46bbf4,0x3115375e,0x3be63b1a,
0x39963ae9,0x39ba3807,0xbbddbb30,0x31db3705,0x336537b7,0x3bc93b02,0xbb80bbf8,0xb593ad7e,0xb4d5a8b6,0x3ba03bff,0xb900ba7c,0xba3fb8b0,0xb9feb85d,0x394d3ab5,0xb04eb64e,0xbbedbb5a,
0xabd9b475,0xbbfcbbaf,0x3bed3bf8,0x304ead7e,0x35f13115,0xbb6ebbe6,0x3ab53b80,0x385d3593,0x39dc3887,0xb972ba99,0x38323996,0x3ad039ba,0x3ba03ae9,0xb4d5b807,0x2f0e3534,0x3bf43b91,
0xb8d8b75e,0x3a5e3b1a,0xbb30bbaf,0xb705b475,0xbab5b9dc,0x385d3972,0xb996ba7c,0xb9bab8b0,0xbbc9bb5a,0x3365364e,0xb6aab887,0xbb46ba99,0xbbf4bbfc,0xaf0e2bd9,0xad7eb414,0xbbf8bbbc,
0x3bd43b91,0xb2a1b534,0x39ba3a5e,0x399638d8,0x3bff3bf8,0x28b6ad7e,0x38323900,0x3ad03a3f,0x3baf3be6,0x34753115,0x34d536aa,0x3ba03b46,0x3ae93b5a,0x3807364e,0x2bd931db,0x3bfc3bdd,
0xbb02bb46,0xb7b7b6aa,0xb75eb832,0xbb1abad0,0xba5ebab5,0xb8d8b85d,0xb534b64e,0xbb91bb5a,0xb996b9fe,0xb9bab94d,0xb1dbb414,0xbbddbbbc,0xb8b0b927,0xba7cba1f,0xa8b6af0e,0xbbffbbf4,
0x359335f1,0x3b803b6e,0x311531db,0x3be63bdd,0x34d53534,0x3ba03b91,0x2f0e304e,0x3bf43bed,0x34143475,0x3bbc3baf,0x2bd92d7e,0x3bfc3bf8,0x32a13365,0x3bd43bc9,0x224828b6,0x3c003bff,
0x40000,0x60002,0xc0008,0xe000a,0x380034,0x3a0036,0x40003c,0x42003e,0x6c0068,0x6e006a,0x740070,0x760072,0xa0009c,0xa2009e,0xa800a4,0xaa00a6,
0xd400d0,0xd600d2,0xdc00d8,0xde00da,0x1080104,0x10a0106,0x110010c,0x112010e,0x13c0138,0x13e013a,0x1440140,0x1460142,0x170016c,0x172016e,0x1780174,0x17a0176,
0x1a401a0,0x1a601a2,0x1ac01a8,0x1ae01aa,0x1d801d4,0x1da01d6,0x1e001dc,0x1e201de,0x20c0208,0x20e020a,0x2140210,0x2160212,0x240023c,0x242023e,0x2480244,0x24a0246,
0x2740270,0x2760272,0x27c0278,0x27e027a,0x2a802a4,0x2aa02a6,0x2b002ac,0x2b202ae,0x2dc02d8,0x2de02da,0x2e402e0,0x2e602e2,0x310030c,0x312030e,0x3180314,0x31a0316,
0x3440340,0x3460342,0x34c0348,0x34e034a,0x3780374,0x37a0376,0x380037c,0x382037e,0x3ac03a8,0x3ae03aa,0x3b403b0,0x3b603b2,0x3e003dc,0x3e203de,0x3e803e4,0x3ea03e6,
0x4140410,0x4160412,0x41c0418,0x41e041a,0x4480444,0x44a0446,0x450044c,0x452044e,0x47c0478,0x47e047a,0x4840480,0x4860482,0x4b004ac,0x4b204ae,0x4b804b4,0x4ba04b6,
0x4e404e0,0x4e604e2,0x4ec04e8,0x4ee04ea,0x5180514,0x51a0516,0x520051c,0x522051e,0x54c0548,0x54e054a,0x5540550,0x5560552,0x580057c,0x582057e,0x5880584,0x58a0586,
0x5b405b0,0x5b605b2,0x5bc05b8,0x5be05ba,0x5e805e4,0x5ea05e6,0x5f005ec,0x5f205ee,0x61c0618,0x61e061a,0x6240620,0x6260622,0x650064c,0x652064e,0x6580654,0x65a0656,
0x140010,0x160012,0x120010,0x440012,0x480044,0x4a0046,0x460044,0x780046,0x7c0078,0x7e007a,0x7a0078,0xac007a,0xb000ac,0xb200ae,0xae00ac,0xe000ae,
0xe400e0,0xe600e2,0xe200e0,0x11400e2,0x1180114,0x11a0116,0x1160114,0x1480116,0x14c0148,0x14e014a,0x14a0148,0x17c014a,0x180017c,0x182017e,0x17e017c,0x1b0017e,
0x1b401b0,0x1b601b2,0x1b201b0,0x1e401b2,0x1e801e4,0x1ea01e6,0x1e601e4,0x21801e6,0x21c0218,0x21e021a,0x21a0218,0x24c021a,0x250024c,0x252024e,0x24e024c,0x280024e,
0x2840280,0x2860282,0x2820280,0x2b40282,0x2b802b4,0x2ba02b6,0x2b602b4,0x2e802b6,0x2ec02e8,0x2ee02ea,0x2ea02e8,0x31c02ea,0x320031c,0x322031e,0x31e031c,0x350031e,
0x3540350,0x3560352,0x3520350,0x3840352,0x3880384,0x38a0386,0x3860384,0x3b80386,0x3bc03b8,0x3be03ba,0x3ba03b8,0x3ec03ba,0x3f003ec,0x3f203ee,0x3ee03ec,0x42003ee,
0x4240420,0x4260422,0x4220420,0x4540422,0x4580454,0x45a0456,0x4560454,0x4880456,0x48c0488,0x48e048a,0x48a0488,0x4bc048a,0x4c004bc,0x4c204be,0x4be04bc,0x4f004be,
0x4f404f0,0x4f604f2,0x4f204f0,0x52404f2,0x5280524,0x52a0526,0x5260524,0x5580526,0x55c0558,0x55e055a,0x55a0558,0x58c055a,0x590058c,0x592058e,0x58e058c,0x5c0058e,
0x5c405c0,0x5c605c2,0x5c205c0,0x5f405c2,0x5f805f4,0x5fa05f6,0x5f605f4,0x62805f6,0x62c0628,0x62e062a,0x62a0628,0x65c062a,0x660065c,0x662065e,0x65e065c,0x18065e,
0x180018,0x4c001a,0x1a0018,0x4c001a,0x4c004c,0x80004e,0x4e004c,0x80004e,0x800080,0xb40082,0x820080,0xb40082,0xb400b4,0xe800b6,0xb600b4,0xe800b6,
0xe800e8,0x11c00ea,0xea00e8,0x11c00ea,0x11c011c,0x150011e,0x11e011c,0x150011e,0x1500150,0x1840152,0x1520150,0x1840152,0x1840184,0x1b80186,0x1860184,0x1b80186,
0x1b801b8,0x1ec01ba,0x1ba01b8,0x1ec01ba,0x1ec01ec,0x22001ee,0x1ee01ec,0x22001ee,0x2200220,0x2540222,0x2220220,0x2540222,0x2540254,0x2880256,0x2560254,0x2880256,
0x2880288,0x2bc028a,0x28a0288,0x2bc028a,0x2bc02bc,0x2f002be,0x2be02bc,0x2f002be,0x2f002f0,0x32402f2,0x2f202f0,0x32402f2,0x3240324,0x3580326,0x3260324,0x3580326,
0x3580358,0x38c035a,0x35a0358,0x38c035a,0x38c038c,0x3c0038e,0x38e038c,0x3c0038e,0x3c003c0,0x3f403c2,0x3c203c0,0x3f403c2,0x3f403f4,0x42803f6,0x3f603f4,0x42803f6,
0x4280428,0x45c042a,0x42a0428,0x45c042a,0x45c045c,0x490045e,0x45e045c,0x490045e,0x4900490,0x4c40492,0x4920490,0x4c40492,0x4c404c4,0x4f804c6,0x4c604c4,0x4f804c6,
0x4f804f8,0x52c04fa,0x4fa04f8,0x52c04fa,0x52c052c,0x560052e,0x52e052c,0x560052e,0x5600560,0x5940562,0x5620560,0x5940562,0x5940594,0x5c80596,0x5960594,0x5c80596,
0x5c805c8,0x5fc05ca,0x5ca05c8,0x5fc05ca,0x5fc05fc,0x63005fe,0x5fe05fc,0x63005fe,0x6300630,0x6640632,0x6320630,0x6640632,0x6640664,0x1c0666,0x6660664,0x1c0666,
0x1c001c,0x50001e,0x1e001c,0x50001e,0x500050,0x840052,0x520050,0x840052,0x840084,0xb80086,0x860084,0xb80086,0xb800b8,0xec00ba,0xba00b8,0xec00ba,
0xec00ec,0x12000ee,0xee00ec,0x12000ee,0x1200120,0x1540122,0x1220120,0x1540122,0x1540154,0x1880156,0x1560154,0x1880156,0x1880188,0x1bc018a,0x18a0188,0x1bc018a,
0x1bc01bc,0x1f001be,0x1be01bc,0x1f001be,0x1f001f0,0x22401f2,0x1f201f0,0x22401f2,0x2240224,0x2580226,0x2260224,0x2580226,0x2580258,0x28c025a,0x25a0258,0x28c025a,
0x28c028c,0x2c0028e,0x28e028c,0x2c0028e,0x2c002c0,0x2f402c2,0x2c202c0,0x2f402c2,0x2f402f4,0x32802f6,0x2f602f4,0x32802f6,0x3280328,0x35c032a,0x32a0328,0x35c032a,
0x35c035c,0x390035e,0x35e035c,0x390035e,0x3900390,0x3c40392,0x3920390,0x3c40392,0x3c403c4,0x3f803c6,0x3c603c4,0x3f803c6,0x3f803f8,0x42c03fa,0x3fa03f8,0x42c03fa,
0x42c042c,0x460042e,0x42e042c,0x460042e,0x4600460,0x4940462,0x4620460,0x4940462,0x4940494,0x4c80496,0x4960494,0x4c80496,0x4c804c8,0x4fc04ca,0x4ca04c8,0x4fc04ca,
0x4fc04fc,0x53004fe,0x4fe04fc,0x53004fe,0x5300530,0x5640532,0x5320530,0x5640532,0x5640564,0x5980566,0x5660564,0x5980566,0x5980598,0x5cc059a,0x59a0598,0x5cc059a,
0x5cc05cc,0x60005ce,0x5ce05cc,0x60005ce,0x6000600,0x6340602,0x6020600,0x6340602,0x6340634,0x6680636,0x6360634,0x6680636,0x6680668,0x20066a,0x66a0668,0x20066a,
0x5d605d6,0x60a05d6,0x5d605d6,0x60a060a,0x60a060a,0x63e063e,0x60a060a,0x63e063e,0x63e063e,0x672063e,0x63e063e,0x6720672,0x6720672,0x280028,0x6720672,0x280028,
0x5060506,0x53a0506,0x5060506,0x53a053a,0x53a053a,0x56e056e,0x53a053a,0x56e056e,0x56e056e,0x5a2056e,0x56e056e,0x5a205a2,0x5a205a2,0x5d605d6,0x5a205a2,0x5d605d6,
0x4360436,0x46a0436,0x4360436,0x46a046a,0x46a046a,0x49e049e,0x46a046a,0x49e049e,0x49e049e,0x4d2049e,0x49e049e,0x4d204d2,0x4d204d2,0x5060506,0x4d204d2,0x5060506,
0x3660366,0x39a0366,0x3660366,0x39a039a,0x39a039a,0x3ce03ce,0x39a039a,0x3ce03ce,0x3ce03ce,0x40203ce,0x3ce03ce,0x4020402,0x4020402,0x4360436,0x4020402,0x4360436,
0x2960296,0x2ca0296,0x2960296,0x2ca02ca,0x2ca02ca,0x2fe02fe,0x2ca02ca,0x2fe02fe,0x2fe02fe,0x33202fe,0x2fe02fe,0x3320332,0x3320332,0x3660366,0x3320332,0x3660366,
0x1c601c6,0x1fa01c6,0x1c601c6,0x1fa01fa,0x1fa01fa,0x22e022e,0x1fa01fa,0x22e022e,0x22e022e,0x262022e,0x22e022e,0x2620262,0x2620262,0x2960296,0x2620262,0x2960296,
0xf600f6,0x12a00f6,0xf600f6,0x12a012a,0x12a012a,0x15e015e,0x12a012a,0x15e015e,0x15e015e,0x192015e,0x15e015e,0x1920192,0x1920192,0x1c601c6,0x1920192,0x1c601c6,
0x260026,0x5a0026,0x260026,0x5a005a,0x5a005a,0x8e008e,0x5a005a,0x8e008e,0x8e008e,0xc2008e,0x8e008e,0xc200c2,0xc200c2,0xf600f6,0xc200c2,0xf600f6,
0x5d405d4,0x60805d4,0x5d405d4,0x6080608,0x6080608,0x63c063c,0x6080608,0x63c063c,0x63c063c,0x670063c,0x63c063c,0x6700670,0x6700670,0x260026,0x6700670,0x260026,
0x5040504,0x5380504,0x5040504,0x5380538,0x5380538,0x56c056c,0x5380538,0x56c056c,0x56c056c,0x5a0056c,0x56c056c,0x5a005a0,0x5a005a0,0x5d405d4,0x5a005a0,0x5d405d4,
0x4340434,0x4680434,0x4340434,0x4680468,0x4680468,0x49c049c,0x4680468,0x49c049c,0x49c049c,0x4d0049c,0x49c049c,0x4d004d0,0x4d004d0,0x5040504,0x4d004d0,0x5040504,
0x3640364,0x3980364,0x3640364,0x3980398,0x3980398,0x3cc03cc,0x3980398,0x3cc03cc,0x3cc03cc,0x40003cc,0x3cc03cc,0x4000400,0x4000400,0x4340434,0x4000400,0x4340434,
0x2940294,0x2c80294,0x2940294,0x2c802c8,0x2c802c8,0x2fc02fc,0x2c802c8,0x2fc02fc,0x2fc02fc,0x33002fc,0x2fc02fc,0x3300330,0x3300330,0x3640364,0x3300330,0x3640364,
0x1c401c4,0x1f801c4,0x1c401c4,0x1f801f8,0x1f801f8,0x22c022c,0x1f801f8,0x22c022c,0x22c022c,0x260022c,0x22c022c,0x2600260,0x2600260,0x2940294,0x2600260,0x2940294,
0xf400f4,0x12800f4,0xf400f4,0x1280128,0x1280128,0x15c015c,0x1280128,0x15c015c,0x15c015c,0x190015c,0x15c015c,0x1900190,0x1900190,0x1c401c4,0x1900190,0x1c401c4,
0x240024,0x580024,0x240024,0x580058,0x580058,0x8c008c,0x580058,0x8c008c,0x8c008c,0xc0008c,0x8c008c,0xc000c0,0xc000c0,0xf400f4,0xc000c0,0xf400f4,
0x5d205d2,0x60605d2,0x5d205d2,0x6060606,0x6060606,0x63a063a,0x6060606,0x63a063a,0x63a063a,0x66e063a,0x63a063a,0x66e066e,0x66e066e,0x240024,0x66e066e,0x240024,
0x5020502,0x5360502,0x5020502,0x5360536,0x5360536,0x56a056a,0x5360536,0x56a056a,0x56a056a,0x59e056a,0x56a056a,0x59e059e,0x59e059e,0x5d205d2,0x59e059e,0x5d205d2,
0x4320432,0x4660432,0x4320432,0x4660466,0x4660466,0x49a049a,0x4660466,0x49a049a,0x49a049a,0x4ce049a,0x49a049a,0x4ce04ce,0x4ce04ce,0x5020502,0x4ce04ce,0x5020502,
0x3620362,0x3960362,0x3620362,0x3960396,0x3960396,0x3ca03ca,0x3960396,0x3ca03ca,0x3ca03ca,0x3fe03ca,0x3ca03ca,0x3fe03fe,0x3fe03fe,0x4320432,0x3fe03fe,0x4320432,
0x2920292,0x2c60292,0x2920292,0x2c602c6,0x2c602c6,0x2fa02fa,0x2c602c6,0x2fa02fa,0x2fa02fa,0x32e02fa,0x2fa02fa,0x32e032e,0x32e032e,0x3620362,0x32e032e,0x3620362,
0x1c201c2,0x1f601c2,0x1c201c2,0x1f601f6,0x1f601f6,0x22a022a,0x1f601f6,0x22a022a,0x22a022a,0x25e022a,0x22a022a,0x25e025e,0x25e025e,0x2920292,0x25e025e,0x2920292,
0xf200f2,0x12600f2,0xf200f2,0x1260126,0x1260126,0x15a015a,0x1260126,0x15a015a,0x15a015a,0x18e015a,0x15a015a,0x18e018e,0x18e018e,0x1c201c2,0x18e018e,0x1c201c2,
0x220022,0x560022,0x220022,0x560056,0x560056,0x8a008a,0x560056,0x8a008a,0x8a008a,0xbe008a,0x8a008a,0xbe00be,0xbe00be,0xf200f2,0xbe00be,0xf200f2,
0x5d005d0,0x60405d0,0x5d005d0,0x6040604,0x6040604,0x6380638,0x6040604,0x6380638,0x6380638,0x66c0638,0x6380638,0x66c066c,0x66c066c,0x220022,0x66c066c,0x220022,
0x5000500,0x5340500,0x5000500,0x5340534,0x5340534,0x5680568,0x5340534,0x5680568,0x5680568,0x59c0568,0x5680568,0x59c059c,0x59c059c,0x5d005d0,0x59c059c,0x5d005d0,
0x4300430,0x4640430,0x4300430,0x4640464,0x4640464,0x4980498,0x4640464,0x4980498,0x4980498,0x4cc0498,0x4980498,0x4cc04cc,0x4cc04cc,0x5000500,0x4cc04cc,0x5000500,
0x3600360,0x3940360,0x3600360,0x3940394,0x3940394,0x3c803c8,0x3940394,0x3c803c8,0x3c803c8,0x3fc03c8,0x3c803c8,0x3fc03fc,0x3fc03fc,0x4300430,0x3fc03fc,0x4300430,
0x2900290,0x2c40290,0x2900290,0x2c402c4,0x2c402c4,0x2f802f8,0x2c402c4,0x2f802f8,0x2f802f8,0x32c02f8,0x2f802f8,0x32c032c,0x32c032c,0x3600360,0x32c032c,0x3600360,
0x1c001c0,0x1f401c0,0x1c001c0,0x1f401f4,0x1f401f4,0x2280228,0x1f401f4,0x2280228,0x2280228,0x25c0228,0x2280228,0x25c025c,0x25c025c,0x2900290,0x25c025c,0x2900290,
0xf000f0,0x12400f0,0xf000f0,0x1240124,0x1240124,0x1580158,0x1240124,0x1580158,0x1580158,0x18c0158,0x1580158,0x18c018c,0x18c018c,0x1c001c0,0x18c018c,0x1c001c0,
0x200020,0x540020,0x200020,0x540054,0x540054,0x880088,0x540054,0x880088,0x880088,0xbc0088,0x880088,0xbc00bc,0xbc00bc,0xf000f0,0xbc00bc,0xf000f0,
0x30003000,0x30003000,0x30003000,0x30003000,0x30003000,0x30003000,0x30003000,0x30003000,0x0,0x0,0x0,0x0,0x0,0x0,0x0,0x0,
0x30003000,0x30003000,0x30003000,0x30003000,0x30003000,0x30003000,0x30003000,0x30003000,0x0,0x0,0x0,0x0,0x0,0x0,0x0,0x0,
0x2a1f2da8,0xaf64ada8,0xaa1fada8,0x2f642da8,0x2f643000,0xaa1f0000,0xaf64b000,0x2a1f8000,0x2f642da8,0x2a1f2da8,0xaf64ada8,0xaa1fada8,0x2a1f0000,0x2f643000,0xaa1f0000,0xaf64b000,
0x263e2c72,0xafd9aea7,0xa63eac72,0x2fd92ea7,0x2ea72fd9,0xac72a63e,0xaea7afd9,0x2c72263e,0x2fd92ea7,0x263e2c72,0xafd9aea7,0xa63eac72,0x2c72263e,0x2ea72fd9,0xac72a63e,0xaea7afd9,
0x2da80000,0xada80000,0x2da88000,0xada80000,0x2da83000,0xada8b000,0x2da83000,0xada8b000,0x2da83000,0xada8b000,0x2da83000,0xada8b000,0xada80000,0x2da88000,0xada80000,0x2da88000,
0x2f642a1f,0xaf64aa1f,0x2f642a1f,0xaf64aa1f,0x2a1f2f64,0xaa1faf64,0x2a1f2f64,0xaa1faf64,0x2a1f2f64,0xaa1faf64,0x2a1f2f64,0xaa1faf64,0xaf64aa1f,0x2f642a1f,0xaf64aa1f,0x2f642a1f,
0xaa1f2da8,0x2f642da8,0x2a1fada8,0xaf64ada8,0x2f640000,0xaa1fb000,0xaf640000,0x2a1f3000,0xaf64ada8,0xaa1f2da8,0x2f642da8,0x2a1fada8,0x2a1f3000,0x2f648000,0xaa1fb000,0xaf640000,
0xaea7263e,0x2c722fd9,0x2ea7a63e,0xac72afd9,0x2fd92c72,0x263eaea7,0xafd9ac72,0xa63e2ea7,0xac72afd9,0xaea7263e,0x2c722fd9,0x2ea7a63e,0xa63e2ea7,0x2fd92c72,0x263eaea7,0xafd9ac72,
0xada82da8,0xada82da8,0xada82da8,0xada82da8,0x2da8ada8,0x2da8ada8,0x2da8ada8,0x2da8ada8,0x2da82da8,0x2da82da8,0x2da82da8,0x2da82da8,0xada8ada8,0xada8ada8,0xada8ada8,0xada8ada8,
0x3000,0x3000,0x3000,0x80003000,0x8000b000,0x8000b000,0x8000b000,0x8000b000,0x30000000,0x30008000,0x30008000,0x30008000,0xb0000000,0xb0000000,0xb0000000,0xb0000000,
0x2ea7263e,0xac722fd9,0xaea7a63e,0x2c72afd9,0xafd92c72,0xa63eaea7,0x2fd9ac72,0x263e2ea7,0x2c72afd9,0x2ea7263e,0xac722fd9,0xaea7a63e,0x263e2ea7,0xafd92c72,0xa63eaea7,0x2fd9ac72,
0x2f64ada8,0x2a1f2da8,0xaf642da8,0xaa1fada8,0xaa1f3000,0xaf640000,0x2a1fb000,0x2f648000,0xaa1fada8,0x2f64ada8,0x2a1f2da8,0xaf642da8,0x2f640000,0xaa1f3000,0xaf640000,0x2a1fb000,
0xaa1f2f64,0x2a1faf64,0xaa1f2f64,0x2a1faf64,0x2f64aa1f,0xaf642a1f,0x2f64aa1f,0xaf642a1f,0xaf642a1f,0x2f64aa1f,0xaf642a1f,0x2f64aa1f,0xaa1f2f64,0x2a1faf64,0xaa1f2f64,0x2a1faf64,
0x2da80000,0xada80000,0x2da88000,0xada80000,0x2da8b000,0xada83000,0x2da8b000,0xada83000,0xada83000,0x2da8b000,0xada83000,0x2da8b000,0x2da88000,0xada80000,0x2da88000,0xada88000,
0xa63e2c72,0x2fd9aea7,0x263eac72,0xafd92ea7,0xaea72fd9,0x2c72a63e,0x2ea7afd9,0xac72263e,0xafd92ea7,0xa63e2c72,0x2fd9aea7,0x263eac72,0xac72263e,0xaea72fd9,0x2c72a63e,0x2ea7afd9,
0x2f64ada8,0x2a1fada8,0xaf642da8,0xaa1f2da8,0x2a1f0000,0x2f64b000,0xaa1f0000,0xaf643000,0xaa1f2da8,0x2f64ada8,0x2a1fada8,0xaf642da8,0xaf643000,0x2a1f8000,0x2f64b000,0xaa1f8000,
0xb0003000,0xb0003000,0xb0003000,0xb0003000,0xb0003000,0xb0003000,0xb0003000,0xb0003000,0x0,0x8000,0x8000,0x80008000,0x8000,0x8000,0x8000,0x8000,
0x80000000,0x80000000,0x80008000,0x80008000,0x80000000,0x80008000,0x80008000,0x80008000,0xb0003000,0xb0003000,0xb0003000,0xb0003000,0xb0003000,0xb0003000,0xb0003000,0xb0003000,
0xaa1f2da8,0x2f64ada8,0x2a1fada8,0xaf642da8,0xaf643000,0x2a1f0000,0x2f64b000,0xaa1f8000,0xaf642da8,0xaa1f2da8,0x2f64ada8,0x2a1fada8,0xaa1f0000,0xaf643000,0x2a1f0000,0x2f64b000,
0x2fd9aea7,0x263eac72,0xafd92ea7,0xa63e2c72,0x2c72a63e,0x2ea7afd9,0xac72263e,0xaea72fd9,0xa63e2c72,0x2fd9aea7,0x263eac72,0xafd92ea7,0xaea72fd9,0x2c72a63e,0x2ea7afd9,0xac72263e,
0xada80000,0x2da80000,0xada88000,0x2da80000,0xada83000,0x2da8b000,0xada83000,0x2da8b000,0xada83000,0x2da8b000,0xada83000,0x2da8b000,0x2da80000,0xada88000,0x2da88000,0xada88000,
0xaa1f2f64,0x2a1faf64,0xaa1f2f64,0x2a1faf64,0x2f64aa1f,0xaf642a1f,0x2f64aa1f,0xaf642a1f,0x2f64aa1f,0xaf642a1f,0x2f64aa1f,0xaf642a1f,0x2a1faf64,0xaa1f2f64,0x2a1faf64,0xaa1f2f64,
0x2a1f2da8,0xaf642da8,0xaa1fada8,0x2f64ada8,0xaf640000,0x2a1fb000,0x2f640000,0xaa1f3000,0x2f64ada8,0x2a1f2da8,0xaf642da8,0xaa1fada8,0xaa1f3000,0xaf648000,0x2a1fb000,0x2f640000,
0x2c72afd9,0x2ea7263e,0xac722fd9,0xaea7a63e,0x263e2ea7,0xafd92c72,0xa63eaea7,0x2fd9ac72,0xaea7a63e,0x2c72afd9,0x2ea7263e,0xac722fd9,0x2fd9ac72,0x263e2ea7,0xafd92c72,0xa63eaea7,
0x2da8ada8,0x2da8ada8,0x2da8ada8,0x2da8ada8,0xada82da8,0xada82da8,0xada82da8,0xada82da8,0x2da82da8,0x2da82da8,0x2da82da8,0x2da82da8,0xada8ada8,0xada8ada8,0xada8ada8,0xada8ada8,
0x80003000,0x80003000,0x80003000,0x3000,0xb000,0x8000b000,0xb000,0xb000,0xb0000000,0xb0008000,0xb0008000,0xb0008000,0x30000000,0x30000000,0x30000000,0x30008000,
0x2c722fd9,0x2ea7a63e,0xac72afd9,0xaea7263e,0x263eaea7,0xafd9ac72,0xa63e2ea7,0x2fd92c72,0xaea7263e,0x2c722fd9,0x2ea7a63e,0xac72afd9,0x2fd92c72,0x263eaea7,0xafd9ac72,0xa63e2ea7,
0xaf64ada8,0xaa1f2da8,0x2f642da8,0x2a1fada8,0x2a1f3000,0x2f648000,0xaa1fb000,0xaf648000,0x2a1fada8,0xaf64ada8,0xaa1f2da8,0x2f642da8,0xaf640000,0x2a1f3000,0x2f648000,0xaa1fb000,
0x2f642a1f,0xaf64aa1f,0x2f642a1f,0xaf64aa1f,0x2a1f2f64,0xaa1faf64,0x2a1f2f64,0xaa1faf64,0xaa1faf64,0x2a1f2f64,0xaa1faf64,0x2a1f2f64,0x2f642a1f,0xaf64aa1f,0x2f642a1f,0xaf64aa1f,
0xada80000,0x2da80000,0xada88000,0x2da88000,0xada8b000,0x2da83000,0xada8b000,0x2da83000,0x2da83000,0xada8b000,0x2da83000,0xada8b000,0xada88000,0x2da88000,0xada88000,0x2da80000,
0x2fd92ea7,0x263e2c72,0xafd9aea7,0xa63eac72,0x2c72263e,0x2ea72fd9,0xac72a63e,0xaea7afd9,0xa63eac72,0x2fd92ea7,0x263e2c72,0xafd9aea7,0xaea7afd9,0x2c72263e,0x2ea72fd9,0xac72a63e,
0xaf64ada8,0xaa1fada8,0x2f642da8,0x2a1f2da8,0xaa1f0000,0xaf64b000,0x2a1f0000,0x2f643000,0x2a1f2da8,0xaf64ada8,0xaa1fada8,0x2f642da8,0x2f643000,0xaa1f8000,0xaf64b000,0x2a1f0000,
0x80008000,0x80008000,0x80008000,0x80008000,0x80008000,0x80008000,0x80008000,0x80008000,0x30003000,0x30003000,0x30003000,0x30003000,0x30003000,0x30003000,0x30003000,0x30003000,
0x80008000,0x80008000,0x80008000,0x80008000,0x80008000,0x80008000,0x80008000,0x80008000,0x30003000,0x30003000,0x30003000,0x30003000,0x30003000,0x30003000,0x30003000,0x30003000,
0xaf64ada8,0xaa1fada8,0x2f642da8,0x2a1f2da8,0xaa1f8000,0xaf64b000,0x2a1f8000,0x2f643000,0x2a1f2da8,0xaf64ada8,0xaa1fada8,0x2f642da8,0x2f643000,0xaa1f0000,0xaf64b000,0x2a1f8000,
0xafd9aea7,0xa63eac72,0x2fd92ea7,0x263e2c72,0xac72a63e,0xaea7afd9,0x2c72263e,0x2ea72fd9,0x263e2c72,0xafd9aea7,0xa63eac72,0x2fd92ea7,0x2ea72fd9,0xac72a63e,0xaea7afd9,0x2c72263e,
0x2da83000,0xada8b000,0x2da83000,0xada8b000,0xada80000,0x2da88000,0xada80000,0x2da88000,0xada88000,0x2da88000,0xada80000,0x2da88000,0xada8b000,0x2da83000,0xada8b000,0x2da83000,
0x2a1f2f64,0xaa1faf64,0x2a1f2f64,0xaa1faf64,0xaf64aa1f,0x2f642a1f,0xaf64aa1f,0x2f642a1f,0xaf64aa1f,0x2f642a1f,0xaf64aa1f,0x2f642a1f,0xaa1faf64,0x2a1f2f64,0xaa1faf64,0x2a1f2f64,
0xaf64ada8,0xaa1f2da8,0x2f642da8,0x2a1fada8,0x2a1f3000,0x2f648000,0xaa1fb000,0xaf640000,0x2a1fada8,0xaf64ada8,0xaa1f2da8,0x2f642da8,0xaf648000,0x2a1f3000,0x2f648000,0xaa1fb000,
0xac72afd9,0xaea7263e,0x2c722fd9,0x2ea7a63e,0xa63e2ea7,0x2fd92c72,0x263eaea7,0xafd9ac72,0x2ea7a63e,0xac72afd9,0xaea7263e,0x2c722fd9,0xafd9ac72,0xa63e2ea7,0x2fd92c72,0x263eaea7,
0xada8ada8,0xada8ada8,0xada8ada8,0xada8ada8,0x2da82da8,0x2da82da8,0x2da82da8,0x2da82da8,0xada82da8,0xada82da8,0xada82da8,0xada82da8,0x2da8ada8,0x2da8ada8,0x2da8ada8,0x2da8ada8,
0xb0008000,0xb0000000,0xb0000000,0xb0000000,0x30008000,0x30008000,0x30008000,0x30008000,0x3000,0x3000,0x3000,0x80003000,0x8000b000,0x8000b000,0x8000b000,0x8000b000,
0xac722fd9,0xaea7a63e,0x2c72afd9,0x2ea7263e,0xa63eaea7,0x2fd9ac72,0x263e2ea7,0xafd92c72,0x2ea7263e,0xac722fd9,0xaea7a63e,0x2c72afd9,0xafd92c72,0xa63eaea7,0x2fd9ac72,0x263e2ea7,
0x2a1f2da8,0xaf642da8,0xaa1fada8,0x2f64ada8,0xaf648000,0x2a1fb000,0x2f648000,0xaa1f3000,0x2f64ada8,0x2a1f2da8,0xaf642da8,0xaa1fada8,0xaa1f3000,0xaf640000,0x2a1fb000,0x2f648000,
0xaf642a1f,0x2f64aa1f,0xaf642a1f,0x2f64aa1f,0xaa1f2f64,0x2a1faf64,0xaa1f2f64,0x2a1faf64,0x2a1faf64,0xaa1f2f64,0x2a1faf64,0xaa1f2f64,0xaf642a1f,0x2f64aa1f,0xaf642a1f,0x2f64aa1f,
0xada83000,0x2da8b000,0xada83000,0x2da8b000,0x2da88000,0xada80000,0x2da88000,0xada88000,0xada88000,0x2da88000,0xada80000,0x2da88000,0xada83000,0x2da8b000,0xada83000,0x2da8b000,
0xafd92ea7,0xa63e2c72,0x2fd9aea7,0x263eac72,0xac72263e,0xaea72fd9,0x2c72a63e,0x2ea7afd9,0x263eac72,0xafd92ea7,0xa63e2c72,0x2fd9aea7,0x2ea7afd9,0xac72263e,0xaea72fd9,0x2c72a63e,
0xaa1f2da8,0x2f64ada8,0x2a1fada8,0xaf642da8,0xaf643000,0x2a1f8000,0x2f64b000,0xaa1f8000,0xaf642da8,0xaa1f2da8,0x2f64ada8,0x2a1fada8,0xaa1f8000,0xaf643000,0x2a1f8000,0x2f64b000,
0x80008000,0x80000000,0x80000000,0x0,0x80000000,0x80000000,0x80000000,0x80000000,0xb0003000,0xb0003000,0xb0003000,0xb0003000,0xb0003000,0xb0003000,0xb0003000,0xb0003000,
0x3000b000,0x3000b000,0x3000b000,0x3000b000,0x3000b000,0x3000b000,0x3000b000,0x3000b000,0x80000000,0x80000000,0x80008000,0x80008000,0x80000000,0x80008000,0x80008000,0x80008000,
0x2f64ada8,0x2a1fada8,0xaf642da8,0xaa1f2da8,0x2a1f8000,0x2f64b000,0xaa1f8000,0xaf643000,0xaa1f2da8,0x2f64ada8,0x2a1fada8,0xaf642da8,0xaf643000,0x2a1f0000,0x2f64b000,0xaa1f8000,
0x263eac72,0xafd92ea7,0xa63e2c72,0x2fd9aea7,0x2ea7afd9,0xac72263e,0xaea72fd9,0x2c72a63e,0x2fd9aea7,0x263eac72,0xafd92ea7,0xa63e2c72,0x2c72a63e,0x2ea7afd9,0xac72263e,0xaea72fd9,
0xada83000,0x2da8b000,0xada83000,0x2da8b000,0x2da80000,0xada88000,0x2da88000,0xada88000,0x2da88000,0xada88000,0x2da80000,0xada88000,0x2da8b000,0xada83000,0x2da8b000,0xada83000,
0x2f64aa1f,0xaf642a1f,0x2f64aa1f,0xaf642a1f,0x2a1faf64,0xaa1f2f64,0x2a1faf64,0xaa1f2f64,0x2a1faf64,0xaa1f2f64,0x2a1faf64,0xaa1f2f64,0xaf642a1f,0x2f64aa1f,0xaf642a1f,0x2f64aa1f,
0x2f64ada8,0x2a1f2da8,0xaf642da8,0xaa1fada8,0xaa1f3000,0xaf648000,0x2a1fb000,0x2f640000,0xaa1fada8,0x2f64ada8,0x2a1f2da8,0xaf642da8,0x2f648000,0xaa1f3000,0xaf648000,0x2a1fb000,
0xaea7a63e,0x2c72afd9,0x2ea7263e,0xac722fd9,0x2fd9ac72,0x263e2ea7,0xafd92c72,0xa63eaea7,0xac722fd9,0xaea7a63e,0x2c72afd9,0x2ea7263e,0xa63eaea7,0x2fd9ac72,0x263e2ea7,0xafd92c72,
0xada8ada8,0xada8ada8,0xada8ada8,0xada8ada8,0x2da82da8,0x2da82da8,0x2da82da8,0x2da82da8,0x2da8ada8,0x2da8ada8,0x2da8ada8,0x2da8ada8,0xada82da8,0xada82da8,0xada82da8,0xada82da8,
0x30008000,0x30000000,0x30000000,0x30000000,0xb0008000,0xb0008000,0xb0008000,0xb0000000,0x80003000,0x80003000,0x80003000,0x3000,0xb000,0x8000b000,0xb000,0xb000,
0x2ea7a63e,0xac72afd9,0xaea7263e,0x2c722fd9,0xafd9ac72,0xa63e2ea7,0x2fd92c72,0x263eaea7,0x2c722fd9,0x2ea7a63e,0xac72afd9,0xaea7263e,0x263eaea7,0xafd9ac72,0xa63e2ea7,0x2fd92c72,
0xaa1f2da8,0x2f642da8,0x2a1fada8,0xaf64ada8,0x2f648000,0xaa1fb000,0xaf640000,0x2a1f3000,0xaf64ada8,0xaa1f2da8,0x2f642da8,0x2a1fada8,0x2a1f3000,0x2f648000,0xaa1fb000,0xaf648000,
0xaa1faf64,0x2a1f2f64,0xaa1faf64,0x2a1f2f64,0x2f642a1f,0xaf64aa1f,0x2f642a1f,0xaf64aa1f,0xaf64aa1f,0x2f642a1f,0xaf64aa1f,0x2f642a1f,0xaa1faf64,0x2a1f2f64,0xaa1faf64,0x2a1f2f64,
0x2da83000,0xada8b000,0x2da83000,0xada8b000,0xada88000,0x2da88000,0xada88000,0x2da80000,0x2da88000,0xada88000,0x2da80000,0xada80000,0x2da83000,0xada8b000,0x2da83000,0xada8b000,
0xa63eac72,0x2fd92ea7,0x263e2c72,0xafd9aea7,0xaea7afd9,0x2c72263e,0x2ea72fd9,0xac72a63e,0xafd9aea7,0xa63eac72,0x2fd92ea7,0x263e2c72,0xac72a63e,0xaea7afd9,0x2c72263e,0x2ea72fd9,
0x2a1f2da8,0xaf64ada8,0xaa1fada8,0x2f642da8,0x2f643000,0xaa1f8000,0xaf64b000,0x2a1f0000,0x2f642da8,0x2a1f2da8,0xaf64ada8,0xaa1fada8,0x2a1f8000,0x2f643000,0xaa1f8000,0xaf64b000,
0x3c003c00,0x3c003c00,0x3c003c00,0x3c003c00,0x3c003c00,0x3c003c00,0x3c003c00,0x3c003c00,0x80008000,0x80008000,0x80008000,0x80008000,0x80008000,0x80008000,0x80008000,0x80008000,
0x3bd93c00,0x3aa73b64,0x387239a8,0x323e361f,0xb23e0000,0xb872b61f,0xbaa7b9a8,0xbbd9bb64,0xb23e8000,0xb872b61f,0xbaa7b9a8,0xbbd9bb64,0xbbd9bc00,0xbaa7bb64,0xb872b9a8,0xb23eb61f,
0xbb64bc00,0xb61fb9a8,0x361f8000,0x3b6439a8,0x3b643c00,0x361f39a8,0xb61f0000,0xbb64b9a8,0x361f8000,0x3b6439a8,0x3b643c00,0x361f39a8,0xb61f8000,0xbb64b9a8,0xbb64bc00,0xb61fb9a8,
0x38728000,0x3bd93b64,0x323e39a8,0xbaa7b61f,0x3aa73c00,0xb23e361f,0xbbd9b9a8,0xb872bb64,0x3aa73c00,0xb23e361f,0xbbd9b9a8,0xb872bb64,0xb8728000,0xbbd9bb64,0xb23eb9a8,0x3aa7361f,
0xbc008000,0x3c008000,0xbc000000,0x3c008000,0xbc000000,0x3c008000,0xbc000000,0x3c008000,0x3c00,0x8000bc00,0x3c00,0x8000bc00,0x3c00,0x8000bc00,0x80003c00,0x8000bc00,
0xbbd98000,0x3aa7361f,0xb872b9a8,0x323e3b64,0x323ebc00,0xb8723b64,0x3aa7b9a8,0xbbd9361f,0xb23e3c00,0x3872bb64,0xbaa739a8,0x3bd9b61f,0xbbd90000,0x3aa7361f,0xb872b9a8,0x323e3b64,
0x3b648000,0xb61fb9a8,0xb61f3c00,0x3b64b9a8,0xbb648000,0x361f39a8,0x361fbc00,0xbb6439a8,0x361fbc00,0xbb6439a8,0x3b648000,0xb61fb9a8,0xb61f3c00,0x3b64b9a8,0xbb640000,0x361f39a8,
0xb8723c00,0x3bd9b61f,0xb23eb9a8,0xbaa73b64,0xbaa78000,0xb23e3b64,0x3bd9b9a8,0xb872b61f,0x3aa78000,0x323ebb64,0xbbd939a8,0x3872361f,0xb8723c00,0x3bd9b61f,0xb23eb9a8,0xbaa73b64,
0xbbd93c00,0xbaa73b64,0xb87239a8,0xb23e361f,0x323e8000,0x3872b61f,0x3aa7b9a8,0x3bd9bb64,0x323e8000,0x3872b61f,0x3aa7b9a8,0x3bd9bb64,0x3bd9bc00,0x3aa7bb64,0x3872b9a8,0x323eb61f,
0xbc003c00,0xbc003c00,0xbc003c00,0xbc003c00,0xbc003c00,0xbc003c00,0xbc003c00,0xbc003c00,0x80008000,0x80000000,0x80000000,0x80000000,0x80000000,0x80000000,0x0,0x80000000,
0xb8728000,0xbbd93b64,0xb23e39a8,0x3aa7b61f,0xbaa73c00,0x323e361f,0x3bd9b9a8,0x3872bb64,0xbaa73c00,0x323e361f,0x3bd9b9a8,0x3872bb64,0x38728000,0x3bd9bb64,0x323eb9a8,0xbaa7361f,
0x3b64bc00,0x361fb9a8,0xb61f8000,0xbb6439a8,0xbb643c00,0xb61f39a8,0x361f0000,0x3b64b9a8,0xb61f8000,0xbb6439a8,0xbb643c00,0xb61f39a8,0x361f8000,0x3b64b9a8,0x3b64bc00,0x361fb9a8,
0x3bd98000,0xbaa7361f,0x3872b9a8,0xb23e3b64,0xb23ebc00,0x38723b64,0xbaa7b9a8,0x3bd9361f,0x323e3c00,0xb872bb64,0x3aa739a8,0xbbd9b61f,0x3bd98000,0xbaa7361f,0x3872b9a8,0xb23e3b64,
0x3c008000,0xbc008000,0x3c000000,0xbc008000,0x3c000000,0xbc008000,0x3c000000,0xbc000000,0x80003c00,0xbc00,0x80003c00,0x8000bc00,0x80003c00,0xbc00,0x80003c00,0xbc00,
0x38723c00,0xbbd9b61f,0x323eb9a8,0x3aa73b64,0x3aa78000,0x323e3b64,0xbbd9b9a8,0x3872b61f,0xbaa78000,0xb23ebb64,0x3bd939a8,0xb872361f,0x38723c00,0xbbd9b61f,0x323eb9a8,0x3aa73b64,
0xbb640000,0x361fb9a8,0x361f3c00,0xbb64b9a8,0x3b648000,0xb61f39a8,0xb61fbc00,0x3b6439a8,0xb61fbc00,0x3b6439a8,0xbb640000,0x361fb9a8,0x361f3c00,0xbb64b9a8,0x3b648000,0xb61f39a8,
0x39a83c00,0xb9a80000,0xb9a8bc00,0x39a88000,0x39a83c00,0xb9a80000,0xb9a8bc00,0x39a88000,0xb9a88000,0xb9a8bc00,0x39a88000,0x39a83c00,0xb9a80000,0xb9a8bc00,0x39a88000,0x39a83c00,
0x38723c00,0xbbd9b61f,0x323eb9a8,0x3aa73b64,0xbaa70000,0xb23ebb64,0x3bd939a8,0xb872361f,0xbaa78000,0xb23ebb64,0x3bd939a8,0xb872361f,0xb872bc00,0x3bd9361f,0xb23e39a8,0xbaa7bb64,
0xb61fbc00,0x3b6439a8,0xbb640000,0x361fb9a8,0x361f3c00,0xbb64b9a8,0x3b648000,0xb61f39a8,0x3b648000,0xb61f39a8,0xb61fbc00,0x3b6439a8,0xbb648000,0x361fb9a8,0x361f3c00,0xbb64b9a8,
0x3bd98000,0xbaa7361f,0x3872b9a8,0xb23e3b64,0x323e3c00,0xb872bb64,0x3aa739a8,0xbbd9b61f,0x323e3c00,0xb872bb64,0x3aa739a8,0xbbd9b61f,0xbbd98000,0x3aa7b61f,0xb87239a8,0x323ebb64,
0xb9a88000,0xb9a83c00,0x39a88000,0x39a8bc00,0xb9a80000,0xb9a83c00,0x39a88000,0x39a8bc00,0xb9a83c00,0x39a88000,0x39a8bc00,0xb9a80000,0xb9a83c00,0x39a88000,0x39a8bc00,0xb9a88000,
0xb8728000,0xbbd93b64,0xb23e39a8,0x3aa7b61f,0x3aa7bc00,0xb23eb61f,0xbbd939a8,0xb8723b64,0xbaa73c00,0x323e361f,0x3bd9b9a8,0x3872bb64,0xb8728000,0xbbd93b64,0xb23e39a8,0x3aa7b61f,
0x361f8000,0x3b64b9a8,0x3b64bc00,0x361fb9a8,0xb61f8000,0xbb6439a8,0xbb643c00,0xb61f39a8,0x3b64bc00,0x361fb9a8,0xb61f8000,0xbb6439a8,0xbb643c00,0xb61f39a8,0x361f8000,0x3b64b9a8,
0xbbd93c00,0xbaa73b64,0xb87239a8,0xb23e361f,0xb23e8000,0xb872361f,0xbaa739a8,0xbbd93b64,0x323e8000,0x3872b61f,0x3aa7b9a8,0x3bd9bb64,0xbbd93c00,0xbaa73b64,0xb87239a8,0xb23e361f,
0xb8723c00,0x3bd9b61f,0xb23eb9a8,0xbaa73b64,0x3aa78000,0x323ebb64,0xbbd939a8,0x3872361f,0x3aa78000,0x323ebb64,0xbbd939a8,0x3872361f,0x3872bc00,0xbbd9361f,0x323e39a8,0x3aa7bb64,
0xb9a83c00,0x39a80000,0x39a8bc00,0xb9a88000,0xb9a83c00,0x39a88000,0x39a8bc00,0xb9a88000,0x39a88000,0x39a8bc00,0xb9a88000,0xb9a83c00,0x39a80000,0x39a8bc00,0xb9a88000,0xb9a83c00,
0xbbd98000,0x3aa7361f,0xb872b9a8,0x323e3b64,0xb23e3c00,0x3872bb64,0xbaa739a8,0x3bd9b61f,0xb23e3c00,0x3872bb64,0xbaa739a8,0x3bd9b61f,0x3bd98000,0xbaa7b61f,0x387239a8,0xb23ebb64,
0x361fbc00,0xbb6439a8,0x3b640000,0xb61fb9a8,0xb61f3c00,0x3b64b9a8,0xbb648000,0x361f39a8,0xbb648000,0x361f39a8,0x361fbc00,0xbb6439a8,0x3b648000,0xb61fb9a8,0xb61f3c00,0x3b64b9a8,
0x38728000,0x3bd93b64,0x323e39a8,0xbaa7b61f,0xbaa7bc00,0x323eb61f,0x3bd939a8,0x38723b64,0x3aa73c00,0xb23e361f,0xbbd9b9a8,0xb872bb64,0x38728000,0x3bd93b64,0x323e39a8,0xbaa7b61f,
0x39a88000,0x39a83c00,0xb9a88000,0xb9a8bc00,0x39a80000,0x39a83c00,0xb9a80000,0xb9a8bc00,0x39a83c00,0xb9a88000,0xb9a8bc00,0x39a88000,0x39a83c00,0xb9a88000,0xb9a8bc00,0x39a80000,
0x3bd93c00,0x3aa73b64,0x387239a8,0x323e361f,0x323e8000,0x3872361f,0x3aa739a8,0x3bd93b64,0xb23e8000,0xb872b61f,0xbaa7b9a8,0xbbd9bb64,0x3bd93c00,0x3aa73b64,0x387239a8,0x323e361f,
0xb61f8000,0xbb64b9a8,0xbb64bc00,0xb61fb9a8,0x361f8000,0x3b6439a8,0x3b643c00,0x361f39a8,0xbb64bc00,0xb61fb9a8,0x361f0000,0x3b6439a8,0x3b643c00,0x361f39a8,0xb61f8000,0xbb64b9a8,
0x0,0x0,0x0,0x0,0x0,0x0,0x0,0x0,0x3c003c00,0x3c003c00,0x3c003c00,0x3c003c00,0x3c003c00,0x3c003c00,0x3c003c00,0x3c003c00,
0x323e0000,0x3872361f,0x3aa739a8,0x3bd93b64,0x3bd93c00,0x3aa73b64,0x387239a8,0x323e361f,0x3bd93c00,0x3aa73b64,0x387239a8,0x323e361f,0xb23e0000,0xb872b61f,0xbaa7b9a8,0xbbd9bb64,
0xb61f0000,0xbb64b9a8,0xbb64bc00,0xb61fb9a8,0x361f0000,0x3b6439a8,0x3b643c00,0x361f39a8,0xbb64bc00,0xb61fb9a8,0x361f8000,0x3b6439a8,0x3b643c00,0x361f39a8,0xb61f0000,0xbb64b9a8,
0xbaa7bc00,0x323eb61f,0x3bd939a8,0x38723b64,0x38720000,0x3bd93b64,0x323e39a8,0xbaa7b61f,0x38728000,0x3bd93b64,0x323e39a8,0xbaa7b61f,0x3aa73c00,0xb23e361f,0xbbd9b9a8,0xb872bb64,
0x3c00,0x8000bc00,0x3c00,0x8000bc00,0x3c00,0x8000bc00,0x80003c00,0x8000bc00,0x3c000000,0xbc000000,0x3c008000,0xbc000000,0x3c008000,0xbc000000,0x3c008000,0xbc000000,
0xb23e3c00,0x3872bb64,0xbaa739a8,0x3bd9b61f,0xbbd90000,0x3aa7361f,0xb872b9a8,0x323e3b64,0x3bd90000,0xbaa7b61f,0x387239a8,0xb23ebb64,0xb23e3c00,0x3872bb64,0xbaa739a8,0x3bd9b61f,
0x361fbc00,0xbb6439a8,0x3b648000,0xb61fb9a8,0xb61f3c00,0x3b64b9a8,0xbb640000,0x361f39a8,0xbb640000,0x361f39a8,0x361fbc00,0xbb6439a8,0x3b640000,0xb61fb9a8,0xb61f3c00,0x3b64b9a8,
0x3aa78000,0x323ebb64,0xbbd939a8,0x3872361f,0xb8723c00,0x3bd9b61f,0xb23eb9a8,0xbaa73b64,0x3872bc00,0xbbd9361f,0x323e39a8,0x3aa7bb64,0x3aa70000,0x323ebb64,0xbbd939a8,0x3872361f,
0xb23e0000,0xb872361f,0xbaa739a8,0xbbd93b64,0xbbd93c00,0xbaa73b64,0xb87239a8,0xb23e361f,0xbbd93c00,0xbaa73b64,0xb87239a8,0xb23e361f,0x323e8000,0x3872b61f,0x3aa7b9a8,0x3bd9bb64,
0x0,0x8000,0x8000,0x8000,0x8000,0x8000,0x80008000,0x8000,0xbc003c00,0xbc003c00,0xbc003c00,0xbc003c00,0xbc003c00,0xbc003c00,0xbc003c00,0xbc003c00,
0x3aa7bc00,0xb23eb61f,0xbbd939a8,0xb8723b64,0xb8720000,0xbbd93b64,0xb23e39a8,0x3aa7b61f,0xb8728000,0xbbd93b64,0xb23e39a8,0x3aa7b61f,0xbaa73c00,0x323e361f,0x3bd9b9a8,0x3872bb64,
0x361f0000,0x3b64b9a8,0x3b64bc00,0x361fb9a8,0xb61f0000,0xbb6439a8,0xbb643c00,0xb61f39a8,0x3b64bc00,0x361fb9a8,0xb61f8000,0xbb6439a8,0xbb643c00,0xb61f39a8,0x361f0000,0x3b64b9a8,
0x323e3c00,0xb872bb64,0x3aa739a8,0xbbd9b61f,0x3bd98000,0xbaa7361f,0x3872b9a8,0xb23e3b64,0xbbd90000,0x3aa7b61f,0xb87239a8,0x323ebb64,0x323e3c00,0xb872bb64,0x3aa739a8,0xbbd9b61f,
0x80003c00,0xbc00,0x80003c00,0x8000bc00,0x80003c00,0xbc00,0x80003c00,0xbc00,0xbc000000,0x3c000000,0xbc008000,0x3c000000,0xbc008000,0x3c000000,0xbc008000,0x3c008000,
0xbaa78000,0xb23ebb64,0x3bd939a8,0xb872361f,0x38723c00,0xbbd9b61f,0x323eb9a8,0x3aa73b64,0xb872bc00,0x3bd9361f,0xb23e39a8,0xbaa7bb64,0xbaa70000,0xb23ebb64,0x3bd939a8,0xb872361f,
0xb61fbc00,0x3b6439a8,0xbb640000,0x361fb9a8,0x361f3c00,0xbb64b9a8,0x3b648000,0xb61f39a8,0x3b648000,0xb61f39a8,0xb61fbc00,0x3b6439a8,0xbb640000,0x361fb9a8,0x361f3c00,0xbb64b9a8,
0x39a80000,0x39a83c00,0xb9a80000,0xb9a8bc00,0x39a88000,0x39a83c00,0xb9a80000,0xb9a8bc00,0x39a83c00,0xb9a80000,0xb9a8bc00,0x39a88000,0x39a83c00,0xb9a80000,0xb9a8bc00,0x39a88000,
0x3aa70000,0x323e3b64,0xbbd9b9a8,0x3872b61f,0x38723c00,0xbbd9b61f,0x323eb9a8,0x3aa73b64,0x38723c00,0xbbd9b61f,0x323eb9a8,0x3aa73b64,0xbaa70000,0xb23ebb64,0x3bd939a8,0xb872361f,
0xbb640000,0x361fb9a8,0x361f3c00,0xbb64b9a8,0x3b640000,0xb61f39a8,0xb61fbc00,0x3b6439a8,0xb61fbc00,0x3b6439a8,0xbb640000,0x361fb9a8,0x361f3c00,0xbb64b9a8,0x3b648000,0xb61f39a8,
0xb23ebc00,0x38723b64,0xbaa7b9a8,0x3bd9361f,0x3bd90000,0xbaa7361f,0x3872b9a8,0xb23e3b64,0x3bd98000,0xbaa7361f,0x3872b9a8,0xb23e3b64,0x323e3c00,0xb872bb64,0x3aa739a8,0xbbd9b61f,
0xb9a83c00,0x39a88000,0x39a8bc00,0xb9a80000,0xb9a83c00,0x39a88000,0x39a8bc00,0xb9a88000,0x39a80000,0x39a8bc00,0xb9a80000,0xb9a83c00,0x39a88000,0x39a8bc00,0xb9a80000,0xb9a83c00,
0xbaa73c00,0x323e361f,0x3bd9b9a8,0x3872bb64,0xb8728000,0xbbd93b64,0xb23e39a8,0x3aa7b61f,0x38720000,0x3bd9bb64,0x323eb9a8,0xbaa7361f,0xbaa73c00,0x323e361f,0x3bd9b9a8,0x3872bb64,
0x3b64bc00,0x361fb9a8,0xb61f8000,0xbb6439a8,0xbb643c00,0xb61f39a8,0x361f8000,0x3b64b9a8,0xb61f0000,0xbb6439a8,0xbb643c00,0xb61f39a8,0x361f0000,0x3b64b9a8,0x3b64bc00,0x361fb9a8,
0x323e8000,0x3872b61f,0x3aa7b9a8,0x3bd9bb64,0xbbd93c00,0xbaa73b64,0xb87239a8,0xb23e361f,0x3bd9bc00,0x3aa7bb64,0x3872b9a8,0x323eb61f,0x323e0000,0x3872b61f,0x3aa7b9a8,0x3bd9bb64,
0xbaa70000,0xb23e3b64,0x3bd9b9a8,0xb872b61f,0xb8723c00,0x3bd9b61f,0xb23eb9a8,0xbaa73b64,0xb8723c00,0x3bd9b61f,0xb23eb9a8,0xbaa73b64,0x3aa78000,0x323ebb64,0xbbd939a8,0x3872361f,
0xb9a80000,0xb9a83c00,0x39a80000,0x39a8bc00,0xb9a88000,0xb9a83c00,0x39a80000,0x39a8bc00,0xb9a83c00,0x39a80000,0x39a8bc00,0xb9a88000,0xb9a83c00,0x39a88000,0x39a8bc00,0xb9a88000,
0x323ebc00,0xb8723b64,0x3aa7b9a8,0xbbd9361f,0xbbd90000,0x3aa7361f,0xb872b9a8,0x323e3b64,0xbbd98000,0x3aa7361f,0xb872b9a8,0x323e3b64,0xb23e3c00,0x3872bb64,0xbaa739a8,0x3bd9b61f,
0x3b640000,0xb61fb9a8,0xb61f3c00,0x3b64b9a8,0xbb640000,0x361f39a8,0x361fbc00,0xbb6439a8,0x361fbc00,0xbb6439a8,0x3b640000,0xb61fb9a8,0xb61f3c00,0x3b64b9a8,0xbb648000,0x361f39a8,
0x3aa73c00,0xb23e361f,0xbbd9b9a8,0xb872bb64,0x38728000,0x3bd93b64,0x323e39a8,0xbaa7b61f,0xb8720000,0xbbd9bb64,0xb23eb9a8,0x3aa7361f,0x3aa73c00,0xb23e361f,0xbbd9b9a8,0xb872bb64,
0x39a83c00,0xb9a88000,0xb9a8bc00,0x39a88000,0x39a83c00,0xb9a88000,0xb9a8bc00,0x39a80000,0xb9a80000,0xb9a8bc00,0x39a80000,0x39a83c00,0xb9a88000,0xb9a8bc00,0x39a88000,0x39a83c00,
0xb23e8000,0xb872b61f,0xbaa7b9a8,0xbbd9bb64,0x3bd93c00,0x3aa73b64,0x387239a8,0x323e361f,0xbbd9bc00,0xbaa7bb64,0xb872b9a8,0xb23eb61f,0xb23e0000,0xb872b61f,0xbaa7b9a8,0xbbd9bb64,
0xbb64bc00,0xb61fb9a8,0x361f0000,0x3b6439a8,0x3b643c00,0x361f39a8,0xb61f8000,0xbb64b9a8,0x361f0000,0x3b6439a8,0x3b643c00,0x361f39a8,0xb61f0000,0xbb64b9a8,0xbb64bc00,0xb61fb9a8,
};
__device__ __align__(1024) bf16 g_x1T[DM * XP];
__device__ __align__(1024) bf16 g_x2T[DM * XP];
__device__ __align__(1024) uint4 g_of[8][16][1280];
__device__ __align__(1024) float g_fs[2][SEQ];

#define TS_SMEM 0
#define TS_DECL
#define TS_ARG
#define TS_PASS
#define TS_PHASE(p)
#define TS(i)
#define TSX(row, i)
#define TS_BEGIN
#define TS_END

struct cplx { float r, i; };
__device__ __forceinline__ cplx cmul(cplx a, cplx b) {
    cplx o;
    o.r = fmaf(a.r, b.r, -a.i * b.i);
    o.i = fmaf(a.r, b.i, a.i * b.r);
    return o;
}
__device__ __forceinline__ cplx csq(cplx a) {
    cplx o;
    o.r = fmaf(a.r, a.r, -a.i * a.i);
    o.i = 2.f * a.r * a.i;
    return o;
}
__device__ __forceinline__ cplx cexp_p(float arl, float ai, float p) {
    float mag = ex2(arl * p);
    float ang = ai * p;
    float n = rintf(ang * 0.15915494309189535f);
    float r = fmaf(n, -6.2831854820251465f, ang);
    r = fmaf(n, 1.7484555e-7f, r);
    cplx o;
    o.r = mag * __cosf(r);
    o.i = mag * __sinf(r);
    return o;
}

__device__ __forceinline__ uint32_t pack2h(float lo, float hi) {
    uint32_t r;
    asm("cvt.rn.f16x2.f32 %0, %1, %2;" : "=r"(r) : "f"(hi), "f"(lo));
    return r;
}
__device__ __forceinline__ uint32_t hmul(uint32_t a, uint32_t b) { uint32_t d; asm("mul.rn.f16x2 %0, %1, %2;" : "=r"(d) : "r"(a), "r"(b)); return d; }
__device__ __forceinline__ uint32_t hfma(uint32_t a, uint32_t b, uint32_t c) { uint32_t d; asm("fma.rn.f16x2 %0, %1, %2, %3;" : "=r"(d) : "r"(a), "r"(b), "r"(c)); return d; }
__device__ __forceinline__ uint32_t hfms(uint32_t a, uint32_t b, uint32_t c) {
    uint32_t d;
    asm("{\n.reg .b32 n;\nneg.f16x2 n, %1;\nfma.rn.f16x2 %0, n, %2, %3;\n}" : "=r"(d) : "r"(a), "r"(b), "r"(c));
    return d;
}
__device__ __forceinline__ uint32_t hadd(uint32_t a, uint32_t b) { uint32_t d; asm("add.rn.f16x2 %0, %1, %2;" : "=r"(d) : "r"(a), "r"(b)); return d; }
__device__ __forceinline__ uint32_t hsub(uint32_t a, uint32_t b) { uint32_t d; asm("sub.rn.f16x2 %0, %1, %2;" : "=r"(d) : "r"(a), "r"(b)); return d; }
__device__ __forceinline__ uint4 ldg_tab(int tab, int t) { return ldg128((const uint4*)c_fft + t + tab * 128); }
__device__ __forceinline__ uint32_t u4(const uint4& v, int i) { return i == 0 ? v.x : i == 1 ? v.y : i == 2 ? v.z : v.w; }
struct cpair { uint32_t r, i; };
__device__ __forceinline__ cpair pmul(cpair p, uint32_t z) {
    const __half2 zv = *reinterpret_cast<const __half2*>(&z), pr = *reinterpret_cast<const __half2*>(&p.r), pi = *reinterpret_cast<const __half2*>(&p.i);
    const __half2 zr = __low2half2(zv), zi = __high2half2(zv);
    const __half2 a = __hfma2(__hneg2(pi), zi, __hmul2(pr, zr)), b = __hfma2(pi, zr, __hmul2(pr, zi));
    return {*reinterpret_cast<const uint32_t*>(&a), *reinterpret_cast<const uint32_t*>(&b)};
}
__device__ __forceinline__ uint32_t packz(cplx z) { return pack2h(z.r, z.i); }
__device__ __forceinline__ void wgmma_kg(float (&d)[24], uint64_t da, uint64_t db, int scale_d) {
    asm volatile("{\n.reg .pred p;\nsetp.ne.b32 p, %26, 0;\n"
                 "wgmma.mma_async.sync.aligned.m64n48k16.f32.f16.f16 "
                 "{%0,%1,%2,%3,%4,%5,%6,%7,%8,%9,%10,%11,%12,%13,%14,%15,%16,%17,%18,%19,%20,%21,%22,%23}, %24, %25, p, 1, 1, 1, 1;\n}\n"
                 : "+f"(d[0]), "+f"(d[1]), "+f"(d[2]), "+f"(d[3]), "+f"(d[4]), "+f"(d[5]), "+f"(d[6]), "+f"(d[7]), "+f"(d[8]), "+f"(d[9]),
                   "+f"(d[10]), "+f"(d[11]), "+f"(d[12]), "+f"(d[13]), "+f"(d[14]), "+f"(d[15]), "+f"(d[16]), "+f"(d[17]), "+f"(d[18]), "+f"(d[19]),
                   "+f"(d[20]), "+f"(d[21]), "+f"(d[22]), "+f"(d[23])
                 : "l"(da), "l"(db), "r"(scale_d));
}

struct SsmParams { const bf16 *lar, *aim, *cre, *cim, *logdt, *dskip; const unsigned* epoch; };
constexpr int KG_TABLES = 6 * 16384, KG_RES = 1664;
struct KgShared { uint32_t kmax[6], kexp[6]; float cinv[6], tap0[6]; };
#define KS(f, i) (ks + (uint32_t)offsetof(KgShared, f) + 4 * (i))
struct KgParams { uint32_t l[3], a[3], r[3], i[3], dt, ds; };

__device__ __forceinline__ bool kg_is_hi(int warp) { return ((warp >> 1) ^ (warp >> 2)) & 1; }
__device__ __forceinline__ void kgen_load(KgParams& kp, int d0, int warp, int lane, const SsmParams& sp) {
    const int d = d0 + min(2 * (warp >> 2) + (warp & 1), 4), idx = d * (NMODE / 2) + lane;
    const bf16 *pr = kg_is_hi(warp) ? sp.cre : sp.lar, *pi = kg_is_hi(warp) ? sp.cim : sp.aim;
    kp.dt = __ldg((const uint16_t*)sp.logdt + d);
#pragma unroll
    for (int j = 0; j < 3; j++) {
        kp.l[j] = __ldg((const uint32_t*)sp.lar + idx + 32 * j); kp.a[j] = __ldg((const uint32_t*)sp.aim + idx + 32 * j);
        kp.r[j] = __ldg((const uint32_t*)pr + idx + 32 * j); kp.i[j] = __ldg((const uint32_t*)pi + idx + 32 * j);
    }
    kp.ds = __ldg((const uint16_t*)sp.dskip + d0 + min(warp >> 1, 4));
}

struct KgAnchors { uint32_t v[8]; };
__device__ __forceinline__ KgAnchors kg_anchor_lo(const KgParams& kp, uint32_t sel, float dt) {
    auto B = [&](uint32_t v) { return __uint_as_float(__byte_perm(v, 0u, sel)); };
    const float arl = -rbf(ex2(B(kp.l[0]) * 1.4426950408889634f)) * dt * 1.4426950408889634f, ai = B(kp.a[0]) * dt;
    const cplx z8 = cexp_p(arl, ai, 8.f), z16 = csq(z8), z24 = cmul(z16, z8), z32 = csq(z16), z64 = csq(z32), z128 = csq(z64), z192 = cmul(z128, z64);
    return {{pack2h(1.f, z8.r), pack2h(0.f, z8.i), pack2h(z16.r, z24.r), pack2h(z16.i, z24.i), packz(z32), packz(z64), packz(z128), packz(z192)}};
}
__device__ __forceinline__ KgAnchors kg_anchor_hi(const KgParams& kp, uint32_t sel, float dt, float cs) {
    auto B = [&](uint32_t v) { return __uint_as_float(__byte_perm(v, 0u, sel)); };
    const float arl = -rbf(ex2(B(kp.l[0]) * 1.4426950408889634f)) * dt * 1.4426950408889634f, ai = B(kp.a[0]) * dt;
    const cplx z1 = cexp_p(arl, -ai, 1.f), z2 = csq(z1), z4 = csq(z2), z256 = cexp_p(arl, -ai, 256.f), z512 = csq(z256), z1024 = csq(z512);
    const cplx H0 = {B(kp.r[0]) * cs, -B(kp.i[0]) * cs}, H4 = cmul(H0, z4);
    return {{pack2h(H0.r, H4.r), pack2h(H0.i, H4.i), packz(z1), packz(z2), packz(z256), packz(z512), packz(z1024), 0u}};
}

template <class Idle>
__device__ __forceinline__ void kgen_tables(KgParams& kp, uint32_t scr, uint32_t dump, uint32_t ks, int warp, int lane, Idle idle TS_ARG) {
    const int wg = warp >> 2, half = warp & 1, sw = lane & 7;
    const bool hi = kg_is_hi(warp);
    TS(23);
    const float dt = rbf(ex2(bf_lo(kp.dt) * 1.4426950408889634f));
    uint32_t sel = (wg == 2 && half) ? 0x3244u : 0x1044u;
    float cs = 0.f;
    KgAnchors an;
    if (hi) {
        uint32_t m = 0;
#pragma unroll
        for (int j = 0; j < 3; j++) m = __vmaxu2(m, __vmaxu2(kp.r[j] & 0x7FFF7FFFu, kp.i[j] & 0x7FFF7FFFu));
        m = __reduce_max_sync(~0u, max(m << 16, m & 0xFFFF0000u));
        const uint32_t e = min(max(__float_as_uint(2.f * dt * __uint_as_float(m)) >> 23, 2u), 252u);
        cs = 2.f * dt * __uint_as_float((253u - e) << 23);
        if (lane == 0) { sts32(KS(cinv, 2 * wg + half), (e + 1u) << 23); sts32(KS(kmax, 2 * wg + half), 0u); }
        an = kg_anchor_hi(kp, sel, dt, cs);
    } else {
        an = kg_anchor_lo(kp, sel, dt);
    }
    float acc[24];
#pragma unroll
    for (int i = 0; i < 24; i++) acc[i] = 0.f;
    uint32_t tb = scr + 2 * wg * 16384 + lane * 128;
    uint64_t da = mkdesc(scr + 2 * wg * 16384, 4096, 1024, 1);
    int flip = 16384;
#pragma unroll 1
    for (int c = wg == 2 ? 1 : 0, step = wg == 2 ? 2 : 1; c < 6; c += step) {
        if (wg < 2) sel ^= 0x2200u;
        if (!hi) {
            if (c & 1) { kp.l[0] = kp.l[1]; kp.l[1] = kp.l[2]; kp.a[0] = kp.a[1]; kp.a[1] = kp.a[2]; }
            cpair p[4];
            p[0] = {an.v[0], an.v[1]}; p[1] = {an.v[2], an.v[3]};
            p[2] = pmul(p[0], an.v[4]); p[3] = pmul(p[1], an.v[4]);
#pragma unroll
            for (int j = 0; j < 4; j++) {
                cpair v[4];
#pragma unroll
                for (int i = 0; i < 4; i++) v[i] = j ? pmul(p[i], an.v[4 + j]) : p[i];
                const uint32_t a = tb + (((4 * half + j) ^ sw) << 4);
                sts128(a, make_uint4(v[0].r, v[1].r, v[2].r, v[3].r));
                sts128(a + 4096, make_uint4(v[0].i, v[1].i, v[2].i, v[3].i));
            }
            an = kg_anchor_lo(kp, sel, dt);
        } else {
            if (c & 1) {
#pragma unroll
                for (int j = 0; j < 2; j++) { kp.l[j] = kp.l[j + 1]; kp.a[j] = kp.a[j + 1]; kp.r[j] = kp.r[j + 1]; kp.i[j] = kp.i[j + 1]; }
            }
            const uint32_t h1 = an.v[2], h2 = an.v[3], h256 = an.v[4], h512 = an.v[5], h1024 = an.v[6];
            cpair p[11];
            p[0] = {an.v[0], an.v[1]};
            p[1] = pmul(p[0], h2); p[2] = pmul(p[0], h1); p[3] = pmul(p[1], h1);
            p[4] = pmul(p[0], h256); p[5] = pmul(p[1], h256); p[6] = pmul(p[0], h512); p[7] = pmul(p[4], h512);
            p[8] = pmul({__byte_perm(p[0].r, p[4].r, 0x5410), __byte_perm(p[0].i, p[4].i, 0x5410)}, h1024);
            p[9] = pmul(p[8], h512); p[10] = pmul(p[8], h1024);
#pragma unroll
            for (int j = 0; j < 3; j++) {
                const uint32_t a = tb + 8192 + (((3 * half + j) ^ sw) << 4);
                sts128(a, make_uint4(p[4 * j].r, p[4 * j + 1].r, p[4 * j + 2].r, p[j < 2 ? 4 * j + 3 : 10].r));
                sts128(a + 4096, make_uint4(p[4 * j].i, p[4 * j + 1].i, p[4 * j + 2].i, p[j < 2 ? 4 * j + 3 : 10].i));
            }
            an = kg_anchor_hi(kp, sel, dt, cs);
        }
        if (c == 0) TS(24);
        if (c == 3) TS(25);
        fence_async_smem();
        wg_wait<0>();
        named_bar(5 + wg, 128);
        wg_fence();
#pragma unroll
        for (int k = 0; k < 4; k++) wgmma_kg(acc, da + k * 128, da + 512 + k * 128, 1);
        wg_commit();
        tb += flip; da += flip >> 4; flip = -flip;
    }
    const bool up = warp & 2;
    const int r = 2 * wg + up, lo0 = 16 * half + (lane >> 2);
    const uint32_t o = dump + r * KG_RES + lo0 * 52 + 4 * (lane & 3);
    const float ci = __uint_as_float(lds32(KS(cinv, r)));
    const float ds = warp <= 8 ? bf_lo(kp.ds) : 0.f;
    TS(26);
    idle();
    wg_wait<0>();
    float v[12], m = 0.f;
#pragma unroll
    for (int j = 0; j < 12; j++) { v[j] = up ? acc[12 + j] : acc[j]; m = fmaxf(m, fabsf(v[j])); }
#pragma unroll
    for (int j = 0; j < 6; j++) sts32(o + (j & 1) * 416 + (j >> 1) * 16, pack2h(v[2 * j], v[2 * j + 1]));
    const uint32_t mm = __reduce_max_sync(~0u, __float_as_uint(m));
    if (lane == 0) {
        asm volatile("red.shared.max.u32 [%0], %1;" ::"r"(KS(kmax, r)), "r"(mm) : "memory");
        if (!half) sts32(KS(tap0, r), __float_as_uint(fmaf(ci, v[0], ds)));
    }
}
#define F_STAG 4
__device__ __forceinline__ void wgmma_h64_rs(uint32_t (&d)[16], const uint4& a, uint64_t db, int scale_d) {
    asm volatile("{\n.reg .pred p;\nsetp.ne.b32 p, %21, 0;\n"
                 "wgmma.mma_async.sync.aligned.m64n64k16.f16.f16.f16 {%0,%1,%2,%3,%4,%5,%6,%7,%8,%9,%10,%11,%12,%13,%14,%15}, {%16,%17,%18,%19}, %20, p, 1, 1, 1;\n}\n"
                 : "+r"(d[0]), "+r"(d[1]), "+r"(d[2]), "+r"(d[3]), "+r"(d[4]), "+r"(d[5]), "+r"(d[6]), "+r"(d[7]), "+r"(d[8]), "+r"(d[9]),
                   "+r"(d[10]), "+r"(d[11]), "+r"(d[12]), "+r"(d[13]), "+r"(d[14]), "+r"(d[15])
                 : "r"(a.x), "r"(a.y), "r"(a.z), "r"(a.w), "l"(db), "r"(scale_d));
}
template <int TB>
__device__ __forceinline__ void wgmma_h32_rs(uint32_t (&d)[8], const uint4& a, uint64_t db, int scale_d) {
    asm volatile("{\n.reg .pred p;\nsetp.ne.b32 p, %13, 0;\n"
                 "wgmma.mma_async.sync.aligned.m64n32k16.f16.f16.f16 {%0,%1,%2,%3,%4,%5,%6,%7}, {%8,%9,%10,%11}, %12, p, 1, 1, %14;\n}\n"
                 : "+r"(d[0]), "+r"(d[1]), "+r"(d[2]), "+r"(d[3]), "+r"(d[4]), "+r"(d[5]), "+r"(d[6]), "+r"(d[7])
                 : "r"(a.x), "r"(a.y), "r"(a.z), "r"(a.w), "l"(db), "r"(scale_d), "n"(TB));
}
__device__ __forceinline__ void wgmma_s1(uint32_t (&d)[16], const uint4& a, uint64_t db, int scale_d) { wgmma_h64_rs(d, a, db, scale_d); }
__device__ __forceinline__ void wgmma_s1(uint32_t (&d)[8], const uint4& a, uint64_t db, int scale_d) { wgmma_h32_rs<1>(d, a, db, scale_d); }
__device__ __forceinline__ void wgmma_s4(float (&d)[32], const uint4& a, uint64_t db, uint32_t meta, int scale_d) {
    asm volatile("{\n.reg .pred p;\nsetp.ne.b32 p, %38, 0;\n"
                 "wgmma.mma_async.sp.sync.aligned.m64n64k32.f32.f16.f16 {%0,%1,%2,%3,%4,%5,%6,%7,%8,%9,%10,%11,%12,%13,%14,%15,%16,%17,%18,%19,%20,%21,%22,%23,%24,%25,%26,%27,%28,%29,%30,%31}, {%32,%33,%34,%35}, %36, %37, 0, p, 1, 1, 1;\n}\n"
                 : "+f"(d[0]), "+f"(d[1]), "+f"(d[2]), "+f"(d[3]), "+f"(d[4]), "+f"(d[5]), "+f"(d[6]), "+f"(d[7]), "+f"(d[8]), "+f"(d[9]), "+f"(d[10]), "+f"(d[11]), "+f"(d[12]), "+f"(d[13]), "+f"(d[14]), "+f"(d[15]), "+f"(d[16]), "+f"(d[17]), "+f"(d[18]), "+f"(d[19]), "+f"(d[20]), "+f"(d[21]), "+f"(d[22]), "+f"(d[23]), "+f"(d[24]), "+f"(d[25]), "+f"(d[26]), "+f"(d[27]), "+f"(d[28]), "+f"(d[29]), "+f"(d[30]), "+f"(d[31])
                 : "r"(a.x), "r"(a.y), "r"(a.z), "r"(a.w), "l"(db), "r"(meta), "r"(scale_d));
}
__device__ __forceinline__ void wgmma_s4(float (&d)[16], const uint4& a, uint64_t db, uint32_t meta, int scale_d) {
    asm volatile("{\n.reg .pred p;\nsetp.ne.b32 p, %22, 0;\n"
                 "wgmma.mma_async.sp.sync.aligned.m64n32k32.f32.f16.f16 {%0,%1,%2,%3,%4,%5,%6,%7,%8,%9,%10,%11,%12,%13,%14,%15}, {%16,%17,%18,%19}, %20, %21, 0, p, 1, 1, 1;\n}\n"
                 : "+f"(d[0]), "+f"(d[1]), "+f"(d[2]), "+f"(d[3]), "+f"(d[4]), "+f"(d[5]), "+f"(d[6]), "+f"(d[7]), "+f"(d[8]), "+f"(d[9]), "+f"(d[10]), "+f"(d[11]), "+f"(d[12]), "+f"(d[13]), "+f"(d[14]), "+f"(d[15])
                 : "r"(a.x), "r"(a.y), "r"(a.z), "r"(a.w), "l"(db), "r"(meta), "r"(scale_d));
}

__device__ __forceinline__ uint32_t& u4r(uint4& v, int i) { return i == 0 ? v.x : i == 1 ? v.y : i == 2 ? v.z : v.w; }

template <int NC>
__device__ __forceinline__ void fft_stage(const uint32_t (&u)[2][4], int c, uint32_t eo, int w, int lane) {
    const int mi = lane >> 3, mj = lane & 7;
    const uint32_t a = eo + (8 * w + mj) * 128 + (((4 * c + mi) ^ mj) << 4);
    stsm_x4(a, hadd(u[0][0], u[1][0]), hadd(u[0][1], u[1][1]), hadd(u[0][2], u[1][2]), hadd(u[0][3], u[1][3]));
    stsm_x4(NC == 2 ? a + 4096 : a ^ 64, hsub(u[0][0], u[1][0]), hsub(u[0][1], u[1][1]), hsub(u[0][2], u[1][2]), hsub(u[0][3], u[1][3]));
}
template <int NC>
__device__ __forceinline__ void kernel_stage(const uint4 (&ko)[2], uint32_t kt, uint32_t ks, int r, uint32_t eo, int w, int lane) {
    uint32_t u[2][2][4], sc[NC], t0[NC];
#pragma unroll
    for (int c = 0; c < NC; c++) {
        auto L = [](uint32_t a) { return __uint_as_float(lds32(a)); };
        const float ci = L(KS(cinv, r + c)), k0 = L(KS(tap0, r + c)) + (NC == 1 ? L(KS(tap0, r + 1)) : 0.f);
        const float mx = fmaxf(ci * (L(KS(kmax, r + c)) + (NC == 1 ? L(KS(kmax, r + 1)) : 0.f) + 0x1p-14f), fabsf(k0));
        const uint32_t e = min(max(__float_as_uint(mx) >> 23, 4u), 250u);
        const float s = __uint_as_float((253u - e) << 23), f = s * ci;
        if (w == 0 && lane == 0) sts32(KS(kexp, r + c), e);
        sc[c] = pack2h(f, f); t0[c] = pack2h(k0 * s, 0.f);
    }
#pragma unroll
    for (int h = 0; h < 2; h++)
#pragma unroll
        for (int j = 0; j < 4; j++) {
            const uint32_t a0 = kt + (u4(ko[h], j) & 0xFFFF), a1 = kt + (u4(ko[h], j) >> 16);
#pragma unroll
            for (int c = 0; c < 2; c++)
                asm volatile("{\n.reg .b16 a, b;\nld.shared.b16 a, [%1];\nld.shared.b16 b, [%2];\nmov.b32 %0, {a, b};\n}"
                             : "=r"(u[c][h][j]) : "r"(a0 + c * KG_RES), "r"(a1 + c * KG_RES) : "memory");
            if (NC == 1) u[0][h][j] = hadd(u[0][h][j], u[1][h][j]);
#pragma unroll
            for (int c = 0; c < NC; c++) {
                u[c][h][j] = hmul(u[c][h][j], sc[c]);
                if (h + j == 0 && w == 0 && lane == 0) u[c][0][0] = __byte_perm(t0[c], u[c][0][0], 0x7610);
            }
        }
#pragma unroll
    for (int c = 0; c < NC; c++) fft_stage<NC>(u[c], c, eo, w, lane);
}

template <int NC, bool SHEAR, class Mid>
__device__ __forceinline__ void fft_forward(const uint4 (&a1)[4], const uint4 (&tw)[4], uint32_t eo, uint32_t s2, uint32_t (&X)[NC][2][8], Mid mid) {
    uint32_t dr[8 * NC], di[8 * NC];
    const uint64_t de = mkdesc(eo, 4096, 1024, 1), d2 = mkdesc(s2, 16, 1024, 1);
    wg_fence();
    wgmma_s1(dr, a1[0], de, 0);
    wgmma_s1(di, a1[2], de + (NC == 2 ? 256 : 4), 0);
    wgmma_s1(dr, a1[1], de + 128, 1);
    wgmma_s1(di, a1[3], de + (NC == 2 ? 384 : 132), 1);
    wg_commit();
    mid();
    wg_wait<0>();
#pragma unroll
    for (int c = 0; c < NC; c++) {
        uint4 zr[2], zi[2];
#pragma unroll
        for (int p = 0; p < 2; p++)
#pragma unroll
            for (int i = 0; i < 4; i++) {
                const uint32_t r = dr[8 * c + 4 * p + i], m = di[8 * c + 4 * p + i], tr = u4(tw[p], i), ti = u4(tw[2 + p], i);
                if (SHEAR) {
                    const uint32_t r1 = hfma(tr, m, r), m1 = hfma(ti, r1, m);
                    u4r(zr[p], i) = hfma(tr, m1, r1); u4r(zi[p], i) = m1;
                } else {
                    u4r(zr[p], i) = hfms(m, ti, hmul(r, tr));
                    u4r(zi[p], i) = hfma(m, tr, hmul(r, ti));
                }
            }
        wg_fence();
        wgmma_h32_rs<0>(X[c][0], zi[0], d2 + 2, 0);
        wgmma_h32_rs<0>(X[c][1], zi[1], d2 + 6, 0);
        wgmma_h32_rs<0>(X[c][0], zr[0], d2, 1);
        wgmma_h32_rs<0>(X[c][1], zr[1], d2 + 4, 1);
        wg_commit();
    }
}

template <int NC, class Idle, class Ready, class Staged>
__device__ __forceinline__ void conv_wg(int ch0, int layer, uint32_t eo, uint32_t zb, uint32_t s23, uint32_t kexp, uint32_t epoch, uint32_t st, uint32_t sbar,
                                        int warp, int lane, uint4 (&a1)[4], uint4 (&tw)[4], Idle idle, Ready ready, Staged staged TS_ARG) {
    const int wg = warp >> 2, w = warp & 3, t = 32 * w + lane, q = lane & 3, mi = lane >> 3, mj = lane & 7;
    auto F = [](uint32_t x) { return __uint_as_float(x); };
    uint32_t KH[NC][2][8];
    TS(2);
    fft_forward<NC, false>(a1, tw, eo, s23, KH, [] {});
    named_bar(1 + wg, 128);
    uint4 a4[4];
#pragma unroll
    for (int i = 0; i < 4; i++) if (NC == 2) { tw[i] = ldg_tab(4 + i, t); a4[i] = ldg_tab(12 + i, t); }
    wg_wait<0>();
    TS(4);
    idle();
    uint2 x[NC][2][2];
    const uint32_t ra[2] = {4u * t, 4u * (t ^ 252)};
    ready();
    TS(5);
    auto xload = [&](int i) {
        const unsigned long long v = ld_ll((const unsigned long long*)(g_x1T + (uint32_t)ch0 * XP + ra[(i >> 1) & 1] + ((i >> 2) * XP + 1024 * (i & 1))));
        x[i >> 2][(i >> 1) & 1][i & 1] = make_uint2((uint32_t)v, (uint32_t)(v >> 32));
    };
#pragma unroll
    for (int i = 0; i < 4 * NC; i++) xload(i);
    TS(6);
    if (NC == 1) {
        uint4 s[8];
        TS(1);
#pragma unroll
        for (int i = 0; i < 8; i++) s[i] = make_uint4(layer, 0, 0, 0);
        int spin = 0;
        uint32_t bad;
        do {
            bad = 0;
#pragma unroll
            for (int i = 0; i < 8; i++)
                if (((s[i].x ^ layer) & 1u) == 0) s[i] = ld_ll4((const uint4*)(g_fs[0] + ra[i >> 2] + (SEQ * (i & 1) + 1024 * ((i >> 1) & 1))));
#pragma unroll
            for (int i = 0; i < 8; i++) bad |= ~(s[i].x ^ layer);
        } while ((bad & 1u) && ++spin < (1 << 18));
#pragma unroll
        for (int i = 0; i < 8; i++) sts128(st + i * 2048 + t * 16, s[i]);
        __syncwarp();
        if (lane == 0) mbar_arrive(sbar + 8 * w);
        TS(14);
    }
    for (int spin = 0; spin < (1 << 18); spin++) {
        uint32_t bad = 0;
#pragma unroll
        for (int i = 0; i < 4 * NC; i++) bad |= ~(x[i >> 2][(i >> 1) & 1][i & 1].x ^ layer);
        if (!(bad & 1u)) break;
#pragma unroll
        for (int i = 0; i < 4 * NC; i++) if (((x[i >> 2][(i >> 1) & 1][i & 1].x ^ layer) & 1u) == 0) xload(i);
    }
    __syncwarp();
#pragma unroll
    for (int i = 0; i < 4; i++) if (NC == 1) { tw[i] = ldg_tab(4 + i, t); a4[i] = ldg_tab(12 + i, t); }
    TS(26);
    if (NC == 2) mbar_wait(sbar + 8 * w, 0);
    staged();
    {
        uint4 s[2][2][2];
        uint32_t u[NC][2][4];
#pragma unroll
        for (int h = 0; h < 2; h++) {
            if (NC == 1 || h == 0) {
#pragma unroll
                for (int i = 4 * h; i < (NC == 1 ? 4 * h + 4 : 8); i++) s[i >> 2][(i >> 1) & 1][i & 1] = lds128(st + i * 2048 + t * 16);
            }
            if (h == 0) TS(7);
#pragma unroll
            for (int c = 0; c < NC; c++)
#pragma unroll
                for (int j = 0; j < 4; j++) {
                    const uint4 &a = s[h][j >> 1][0], &b = s[h][j >> 1][1];
                    const uint32_t xv = (j & 1) ? x[c][h][j >> 1].y : x[c][h][j >> 1].x;
                    u[c][h][j] = pack2h(fmaf(bf_lo(xv), F(u4(a, 2 * (j & 1))), F(u4(b, 2 * (j & 1)))), fmaf(bf_hi(xv), F(u4(a, 2 * (j & 1) + 1)), F(u4(b, 2 * (j & 1) + 1))));
                }
        }
#pragma unroll
        for (int c = 0; c < NC; c++) fft_stage<NC>(u[c], c, eo, w, lane);
    }
    TS(8);
    fence_async_smem();
    TS(9);
    named_bar(1 + wg, 128);
    uint32_t X[NC][2][8], Y[NC][2][8];
    uint32_t oscale[NC];
    fft_forward<NC, true>(a1, tw, eo, s23, X, [&] {
#pragma unroll
        for (int c = 0; c < NC; c++) oscale[c] = (lds32(kexp + 4 * c) + 3u) * 0x00800080u;
        if (layer) {
#pragma unroll
            for (int i = 0; i < 4 * NC; i++) asm volatile("mov.b32 %0, 0;\nmov.b32 %1, 0;" : "=r"(x[i >> 2][(i >> 1) & 1][i & 1].x), "=r"(x[i >> 2][(i >> 1) & 1][i & 1].y));
        }
        TS(3); if (F_STAG >= 2 && NC == 2 && wg == 1) named_bar(10 + w, 64); });
    if (F_STAG == 2 && NC == 2 && wg == 0) asm volatile("bar.arrive %0, 64;" ::"r"(10 + w) : "memory");
    TS(10);
    const uint64_t d3 = mkdesc(s23 + 4096, 16, 1024, 1);
#pragma unroll
    for (int c = 0; c < NC; c++) {
        wg_wait<NC - 1>();
        TS(11 + c);
        uint4 pr[2], pi[2];
#pragma unroll
        for (int i = 0; i < 4; i++) {
            const uint32_t er = X[c][0][i], ei = X[c][0][4 + i], orr = X[c][1][i], oi = X[c][1][4 + i];
            const uint32_t ar = KH[c][0][i], ai = KH[c][0][4 + i], br = KH[c][1][i], bi = KH[c][1][4 + i];
            u4r(pr[0], i) = hfms(bi, oi, hfma(br, orr, hfms(ai, ei, hmul(ar, er))));
            u4r(pi[0], i) = hfma(bi, orr, hfma(br, oi, hfma(ai, er, hmul(ar, ei))));
            u4r(pr[1], i) = hfms(ai, oi, hfma(ar, orr, hfms(bi, ei, hmul(br, er))));
            u4r(pi[1], i) = hfma(ai, orr, hfma(ar, oi, hfma(bi, er, hmul(br, ei))));
        }
        if (F_STAG == 3 + c && NC == 2 && wg == 0) asm volatile("bar.arrive %0, 64;" ::"r"(10 + w), "r"(pr[0].x ^ pr[1].w ^ pi[0].y ^ pi[1].z) : "memory");
        wg_fence();
        wgmma_h32_rs<0>(Y[c][0], pr[0], d3, 0);
        wgmma_h32_rs<0>(Y[c][1], pr[1], d3 + 4, 0);
        wgmma_h32_rs<0>(Y[c][0], pi[0], d3 + 2, 1);
        wgmma_h32_rs<0>(Y[c][1], pi[1], d3 + 6, 1);
        wg_commit();
    }
#pragma unroll
    for (int c = 0; c < NC; c++) {
        if (c + 1 < NC) wg_wait<1>(); else wg_wait<0>();
        TS(13 + c);
        uint32_t zr[2][4], zi[2][4];
#pragma unroll
        for (int p = 0; p < 2; p++)
#pragma unroll
            for (int i = 0; i < 4; i++) {
                const uint32_t r = Y[c][p][i], m = Y[c][p][4 + i], tr = u4(tw[p], i), ti = u4(tw[2 + p], i);
                const uint32_t r1 = hfms(tr, m, r), m1 = hfms(ti, r1, m);
                zr[i & 1][2 * p + (i >> 1)] = hfms(tr, m1, r1);
                zi[i & 1][2 * p + (i >> 1)] = m1;
            }
        const int kr = 4 * (mj >> 1) + (mj & 1) + 2 * (mj >> 2), ki = kr ^ 2;
#pragma unroll
        for (int h = 0; h < 2; h++) {
            const uint32_t a = zb + (2 * w + h) * 2048;
            stsm_x4(a + ki * 128 + (((4 * c + mi) ^ (ki & 7)) << 4), zi[h][0], zi[h][1], zi[h][2], zi[h][3]);
            stsm_x4(a + kr * 128 + (((4 * c + mi) ^ (kr & 7)) << 4), zr[h][0], zr[h][1], zr[h][2], zr[h][3]);
        }
    }
    TS(15);
    fence_async_smem();
    TS(16);
    named_bar(1 + wg, 128);
    TS(17);
    float acc[16 * NC];
    const uint64_t dz = mkdesc(zb, 4096, 1024, 1);
    wg_fence();
#pragma unroll
    for (int ks = 0; ks < 4; ks++) wgmma_s4(acc, a4[ks], dz + ks * 256, 0x44EEEE44u, ks > 0);
    wg_commit();
    const uint32_t fb = ~lds32(epoch);
    uint32_t mk[NC][3];
#pragma unroll
    for (int c = 0; c < NC; c++) {
        const int k = ((ch0 + c) >> 1) & 3;
        mk[c][2] = !layer && k == 2 * q; mk[c][1] = !layer && k == 2 * q + 1; mk[c][0] = mk[c][2] | layer;
    }
    auto mark = [&](uint32_t v, uint32_t m) { return (v & ~m) | (fb & m); };
    const char* dst[2];
    {
        uint32_t l2;
        asm volatile("mov.u32 %0, %%laneid;" : "=r"(l2));
        const char* base = layer ? (const char*)g_of + (uint32_t)(ch0 / 80) * 327680u + (uint32_t)(ch0 % 80) * 256u : (const char*)g_x2T + (uint32_t)ch0 * (XP * 2u);
#pragma unroll
        for (int h = 0; h < 2; h++) {
            const uint32_t v = (32 * w + l2) ^ (h ? 252u : 0u);
            dst[h] = base + (layer ? (v >> 4) * 20480u + (v & 15u) * 16u : v * 8u);
        }
    }
    wg_wait<0>();
    TS(18);
#pragma unroll
    for (int c = 0; c < NC; c++) {
        uint32_t r[2][4];
#pragma unroll
        for (int j = 0; j < 4; j++) {
            const float* d = acc + 4 * (4 * c + j);
            const uint32_t y0 = pack2(d[0] + d[2], d[1] + d[3]), y1 = pack2(d[0] - d[2], d[1] - d[3]);
            asm("fma.rn.bf16x2 %0, %1, %2, %3;" : "=r"(r[0][j]) : "r"(y0), "r"(oscale[c]), "r"((j & 1) ? x[c][0][j >> 1].y : x[c][0][j >> 1].x));
            asm("fma.rn.bf16x2 %0, %1, %2, %3;" : "=r"(r[1][j]) : "r"(y1), "r"(oscale[c]), "r"((j & 1) ? x[c][1][j >> 1].y : x[c][1][j >> 1].x));
        }
#pragma unroll
        for (int h = 0; h < 2; h++)
            asm volatile("{\n.reg .pred p;\n.reg .b128 t;\n.reg .b64 a, b;\nsetp.ne.u32 p, %5, 0;\nmov.b64 a, {%1, %2};\nmov.b64 b, {%3, %4};\nmov.b128 t, {a, b};\n"
                         "@p st.relaxed.gpu.global.b128 [%0], t;\n@!p st.relaxed.gpu.global.b64 [%6], a;\n@!p st.relaxed.gpu.global.b64 [%6 + 2048], b;\n}"
                         ::"l"(dst[h] + c * 256), "r"(mark(r[h][0], mk[c][0])), "r"(mark(r[h][1], mk[c][1])), "r"(mark(r[h][2], mk[c][2])), "r"(mark(r[h][3], mk[c][1])), "r"(layer), "l"(dst[h] + c * XP * 2) : "memory");
    }
    TS(19);
}

#define Q_S0 8
#define R_CONS 192
#define K_CSUN 1
constexpr int K_CSU = K_CSUN;
#define G_MAP 1
#define Q_SP 2
#define A_VLO 4
constexpr int Q_ST = 4;
constexpr int Q_AB = 16384, Q_BB = 30720, Q_SB = Q_AB + Q_BB;
constexpr int Q_EROW = 336;
constexpr int Q_ESLOT = 8 * Q_EROW;
constexpr int Q_EOFF = Q_ST * Q_SB;
constexpr int Q_KG = 2 * Q_SB;
static_assert(3 * Q_ESLOT <= 8192 && Q_KG + KG_TABLES <= Q_EOFF + 4096, "exchange slots, kernel generation");
constexpr int F_EO = Q_EOFF, F_S23 = F_EO + 2 * 8192 + 4096, Q_KDUMP = F_S23 + 8192;
constexpr int Q_MISC = Q_KDUMP + 6 * KG_RES;
__host__ __device__ constexpr int w_grp(int j) { return j < 7 ? 2 * Q_SB + 4096 + j * 12800 : 0; }
constexpr int W_RES = Q_AB;
__device__ __forceinline__ int o_slot(int wg, int s) { return W_RES + (((2 * s + 2) & 7) + wg) * 10240; }
__device__ __forceinline__ int w_out(int wg) { return W_RES + (2 + 3 * wg) * 10240; }
static_assert(W_RES + 8 * 10240 == w_grp(0) && w_grp(6) + 12800 <= Q_EOFF && w_grp(3) <= 3 * Q_SB, "phase W layout");

constexpr int Q_WOT = Q_EOFF + 4096;

__device__ unsigned g_epoch;
__device__ __align__(1024) unsigned g_bar[4][16][32];
__device__ __align__(1024) uint4 g_wop[8][80][10][8];
__device__ __align__(1024) uint4 g_csp[8][16][96];
__device__ __align__(1024) uint4 g_stp[16][8][64];
__device__ __align__(1024) uint4 g_sp2[16][8][8][8];
__device__ __align__(1024) uint4 g_halo[128][2][5][32];

struct Bars { uint64_t full[Q_ST], empty[Q_ST], wfull[3], ex[7], res, go, qdone, prep, ardy, hdone, fdone, idx, att[2], wfree, soon[2], st[4], kfree, staged, xland[2]; };
constexpr int NBAR = sizeof(Bars) / 8;
struct OBars { uint64_t full[8], ready[8], empty[8]; };
struct Misc { float cs[240], mean[2][64], rstd[2][72]; Bars bar[2]; OBars ob; KgShared kg; uint32_t epoch, pad; };
#define MISC(f) (sb + Q_MISC + (uint32_t)offsetof(Misc, f))
constexpr int Q_SMEM = Q_MISC + sizeof(Misc) + TS_SMEM;
__host__ __device__ constexpr int bar_count(int i) {
#define BAR_IS(f) (i == offsetof(Bars, f) / 8)
    return (i >= 4 && i < 8) ? 16 : (BAR_IS(go) || (i >= offsetof(Bars, att) / 8 && i < offsetof(Bars, st) / 8)) ? 4 : BAR_IS(qdone) ? 8 : BAR_IS(prep) ? 96 :
           BAR_IS(hdone) ? 6 : BAR_IS(fdone) ? 3 : BAR_IS(kfree) ? 24 : BAR_IS(staged) ? 2 : 1;
}
__device__ __forceinline__ void grid_wait(const unsigned* c, int n, unsigned target, int lane) {
    const unsigned* p = c + 32 * min(lane, n - 1);
    unsigned v;
    int spin = 0;
    do { asm volatile("ld.relaxed.gpu.global.u32 %0, [%1];" : "=r"(v) : "l"(p) : "memory"); } while (!__all_sync(~0u, (int)(v - target) >= 0) && ++spin < (1 << 18));
    fence_acquire();
}
__device__ __forceinline__ void grid_arrive(unsigned* c) {
    fence_release();
    asm volatile("red.relaxed.gpu.global.add.u32 [%0], 1;" ::"l"(c) : "memory");
}

#define TMAP(n) ([] { const CUtensorMap* p_; asm volatile("{\n.reg .b64 t;\nmov.b64 t, fused_kernel_param_" #n ";\ncvta.param.u64 %0, t;\n}" : "=l"(p_)); return p_; }())
extern "C" __global__ void __launch_bounds__(384, 1)
fused_kernel(const SsmParams sp, const __grid_constant__ CUtensorMap mX0, const __grid_constant__ CUtensorMap mX1, const __grid_constant__ CUtensorMap mW,
             const __grid_constant__ CUtensorMap mWr,
             const __grid_constant__ CUtensorMap mRes0, const __grid_constant__ CUtensorMap mRes1, const __grid_constant__ CUtensorMap mOut,
             const __grid_constant__ CUtensorMap mWo, const __grid_constant__ CUtensorMap mFin, const __grid_constant__ CUtensorMap mResA) {
    extern __shared__ __align__(1024) char smraw[];
    const uint32_t sb = s2u(smraw);
    int tid, warp, lane, bx, rank, blk, hg, rot, c0;
    int role;
    {
        const int c = blockIdx.x >> 1, d = c - 41, r = d >= 21 ? 3 : d >= 14 ? 2 : d >= 7 ? 1 : 0;
        const int gp = c < 4 ? 0 : c <= 40 ? (c + 7) & 7 : d - 7 * r + 1;
        const int k = c < 4 ? c : c <= 40 ? (c >> 3) + (gp == 0 ? 3 : gp >= 3 && gp < 7 ? 0 : -1) : (gp >= 3 ? 5 : 4) + r;
        role = G_MAP == 1 ? 16 * k + 2 * gp + (blockIdx.x & 1) : G_MAP == 2 ? 16 * gp + 2 * k + (blockIdx.x & 1) : blockIdx.x;
    }
    auto indices = [&] {
        asm volatile("mov.u32 %0, %%tid.x;" : "=r"(tid));
        asm volatile("mov.u32 %0, %1;" : "=r"(bx) : "r"(role));
        warp = __shfl_sync(~0u, tid >> 5, 0); lane = tid & 31;
        rank = bx & 1; blk = bx & 15; hg = bx >> 4;
        const int u = ((blk >> 1) + hg) & 7;
        rot = (5 * u) >> 2; c0 = 16 * (u & 3);
    };
    indices();
    TS_DECL;
    TS_BEGIN;
#define EPOCH lds32(MISC(epoch))
    int layer = 0;
    uint32_t bars = MISC(bar);
#define BAR(f) (bars + (uint32_t)offsetof(Bars, f))
    auto chunk = [&](int it, int s0) {
        const int i = it < s0 ? it : it - 2;
        return (it >> 1) == (s0 >> 1) ? rot + (it & 1) : i < rot ? i : i + 2;
    };
    auto osrc_of = [&](int j) { return j == 0 ? hg : j - 1 < hg ? j - 1 : j; };
    auto issue_w = [&](uint32_t bb, int it, int lay) {
        const int half = rank;
        const int s = it & (Q_ST - 1);
        const uint32_t fb = bb + 8 * s, db = sb + s * Q_SB + Q_AB + half * 15360;
        const int k0 = chunk(it, Q_SP * lay) * 64 + half * 32;
#pragma unroll
        for (int p = 0; p < 3; p++) tma2d_mc(db + p * 4096, TMAP(3), p * DM + hg * 80, k0, fb, 3);
        tma3d_mc(db + 12288, TMAP(4), hg * 80 + 64, k0, 0, fb, 3);
    };
    auto issue_x = [&](int it) {
        const int s = it & (Q_ST - 1), kc = chunk(it, Q_SP * layer);
        mbar_expect(BAR(full) + 8 * s, Q_SB);
        tma3d(sb + s * Q_SB, TMAP(1) + layer, (layer ? blk : kc) * 64, (layer ? kc : blk) * 64, 0, BAR(full) + 8 * s);
    };
    {
        KgParams kp;
        const uint32_t epoch0 = ldg32(sp.epoch);
        kgen_load(kp, bx * 5, warp, lane, sp);
        if (warp < 8) {
            cluster_arrive_relaxed();
        } else {
            if (elect_one()) {
                if (warp < 10) { prefetch_tmap(TMAP(3)); prefetch_tmap(TMAP(4)); } else prefetch_tmap(warp == 10 ? TMAP(1) : TMAP(8));
                const uint32_t b0 = bars + (warp >= 10 ? sizeof(Bars) : 0);
                if (warp & 1) {
#pragma unroll
                    for (int i = 0; i < NBAR / 2; i++) mbar_init(b0 + i * 8, bar_count(i));
                } else {
#pragma unroll
                    for (int i = NBAR / 2; i < NBAR; i++) mbar_init(b0 + i * 8, bar_count(i));
                }
                fence_mbar_init();
            }
            __syncwarp();
            cluster_arrive_relaxed();
            TS(29);
            cluster_wait();
            TS(27);
            if (elect_one()) {
                if (warp < 10) {
                    issue_w(BAR(full), warp - 8, 0);
                } else if (warp == 10) {
                    issue_x(0); issue_x(1);
                    prefetch_l2((const char*)c_fft + bx * (sizeof(c_fft) / 128), sizeof(c_fft) / 128);
                } else {
                    mbar_expect(BAR(idx), 8192 + 6400);
                    asm volatile("cp.async.bulk.tensor.4d.shared::cluster.global.mbarrier::complete_tx::bytes [%0], [%1, {0, 0, %3, %4}], [%2];"
                                 ::"r"(sb + Q_WOT), "l"(TMAP(8)), "r"(BAR(idx)), "r"(10 * hg), "r"(5 * blk) : "memory");
                    bulk_g2s(sb + F_S23, c_fft + 18 * 512, 8192, BAR(idx));
                }
            }
            __syncwarp();
            TS(30);
        }
        indices();
        kgen_tables(kp, sb + Q_KG, sb + Q_KDUMP, MISC(kg), warp, lane, [&] { if (warp < 8) cluster_wait(); } TS_PASS);
        __syncwarp();
        if (lane == 0) { mbar_arrive_cta(BAR(kfree), 0); mbar_arrive_cta(BAR(kfree), 1); }
        if (warp >= 8) {
            const int t2 = tid - 256;
            float csum[10];
            if (warp < 11 && elect_one()) {
#pragma unroll
                for (int i = 0; i < 8; i++) mbar_init(MISC(ob) + (warp - 8) * 64 + i * 8, warp == 10 ? 4 : 1);
                fence_mbar_init();
            }
            __syncwarp();
            if (t2 == 0) sts32(MISC(epoch), epoch0);
            if (t2 < 64) stg128(&g_sp2[blk][hg][0][0] + t2, make_uint4(0, 0, 0, 0));
            if (t2 >= 64 && t2 < 80) stg128(&g_of[hg][blk][640 * ((t2 >> 3) & 1) + 8 * (73 + (t2 & 6)) + 6 + (t2 & 1)], make_uint4(epoch0, epoch0, epoch0, epoch0));
#pragma unroll
            for (int i = 0; i < 2; i++)
                if (t2 + 128 * i < 160)
                    stg128(g_x2T + (size_t)(5 * bx + 4 * i + (t2 >> 5)) * XP + 1024 + 32 * (t2 & 30) + 8 * (t2 & 1), make_uint4(epoch0, epoch0, epoch0, epoch0));
            if (t2 >= 120) stg128((uint4*)g_fs + 8 * bx + t2 - 120, make_uint4(0, 0, 0, 0));
            if (t2 < 64) stg128(g_x1T + (size_t)(5 * bx + 4) * XP + 64 * (t2 >> 1) + 48 + 8 * (t2 & 1), make_uint4(0, 0, 0, 0));
#pragma unroll
            for (int i = 0; i < 3; i++)
                if (t2 + 128 * i < 320) stg128(&g_halo[bx][0][0][0] + t2 + 128 * i, make_uint4(0, 0, 0, 0));
            named_bar(13, 128);
            if (warp > 8) {
                const int hw = warp - 9, mi = lane >> 3, mj = lane & 7;
                mbar_wait(BAR(idx), 0);
                if (hw == 2 && elect_one()) { bulk_s2g(&g_wop[hg][5 * blk], sb + Q_WOT, 6400); bulk_commit(); }
                __syncwarp();
                mbar_wait(BAR(full), 0);
                mbar_wait(BAR(full) + 8, 0);
#pragma unroll
                for (int f = 0; f < 10; f++) csum[f] = 0.f;
#pragma unroll K_CSU
                for (int G = 0; G < 5; G++) {
                    const int row = c0 + 40 * rank + 8 * G + mj;
                    const uint32_t b = sb + (row >> 6) * Q_SB + Q_AB + ((row >> 5) & 1) * 15360;
                    uint32_t r[10];
                    ldsm_x4_t(r[0], r[1], r[2], r[3], b + hw * 4096 + (row & 31) * 128 + ((mi ^ mj) << 4));
                    ldsm_x4_t(r[4], r[5], r[6], r[7], b + hw * 4096 + (row & 31) * 128 + (((4 + mi) ^ mj) << 4));
                    ldsm_x2_t(r[8], r[9], b + 12288 + hw * 1024 + (row & 31) * 32 + (((mi & 1) ^ (mj >> 2)) << 4));
#pragma unroll
                    for (int f = 0; f < 10; f++) csum[f] += bf_lo(r[f]) + bf_hi(r[f]);
                }
                const int q = lane & 3;
                float t[3];
#pragma unroll
                for (int j = 0; j < 3; j++) {
                    float v[4];
#pragma unroll
                    for (int k = 0; k < 4; k++) v[k] = 4 * j + k < 10 ? csum[4 * j + k] : 0.f;
                    const float a0 = ((q & 2) ? v[2] : v[0]) + __shfl_xor_sync(~0u, (q & 2) ? v[0] : v[2], 2);
                    const float a1 = ((q & 2) ? v[3] : v[1]) + __shfl_xor_sync(~0u, (q & 2) ? v[1] : v[3], 2);
                    t[j] = ((q & 1) ? a1 : a0) + __shfl_xor_sync(~0u, (q & 1) ? a0 : a1, 1);
                }
                st_ll4(&g_csp[hg][blk][tid - 288], ~EPOCH & 1u, __float_as_uint(t[0]), __float_as_uint(t[1]), __float_as_uint(t[2]));
            }
        }
        TS(1);
    }

    uint4 fa1[4], ftw[4];
    auto conv_tables = [&] {
#pragma unroll
        for (int i = 0; i < 4; i++) { fa1[i] = ldg_tab(i, tid & 127); ftw[i] = ldg_tab(8 + i, tid & 127); }
    };
    auto conv_done = [&] {
        if (layer == 0) {
            named_bar(1 + (warp >> 2), 128);
            if ((tid & 127) == 96) {
                mbar_arrive(BAR(fdone));
                grid_arrive(g_bar[2][hg]);
            }
            __syncwarp();
        }
        TS(20);
    };
    if (warp >= 8) {
    asm volatile("setmaxnreg.dec.sync.aligned.u32 %0;" ::"n"(504 - 2 * R_CONS));
    uint32_t ophase = 0;
#pragma unroll 1
    for (; layer < 2; layer++, bars += sizeof(Bars)) {
        indices();
        TS_PHASE(2 * layer);
        if (warp == 8) {
            if (layer) {
                mbar_wait(BAR(fdone) - sizeof(Bars), 0);
                grid_wait(g_bar[2][0], 8, 48 * (EPOCH + 1), lane);
                fence_async_global();
                TS(10);
            }
            if (elect_one()) {
#pragma unroll 1
                for (int it = 2; it < 10; it++) {
                    if (it >= Q_ST) mbar_wait(BAR(empty) + 8 * (it & (Q_ST - 1)), ((it >> 2) - 1) & 1);
                    else if (layer == 0) mbar_wait(BAR(kfree), 0);
                    if (it == Q_ST + Q_SP * layer) mbar_wait(BAR(hdone), 0);
                    issue_x(it);
                    if (layer == 0 || it >= Q_ST) issue_w(BAR(full), it, layer);
                }
                { prefetch_tmap(TMAP(5) + layer); prefetch_tmap(TMAP(7)); prefetch_tmap(TMAP(10)); }
                if (layer == 0) { mbar_wait(BAR(prep), 0); fence_async_global(); }
#pragma unroll 1
                for (int j = 0; j < 8; j++) {
                    const int b = (j + 1) >> 2;
                    const uint32_t fb = BAR(wfull) + 8 * b;
                    if (j == 0 || j == 3 || j == 7) {
                        mbar_wait(BAR(empty) + 8 * ((2 + b) & 3), b < 2);
                        TS(11 + b);
                        mbar_expect(fb, (b == 0 ? 3 : b == 1 ? 4 : 1) * 12800);
                    }
                    bulk_g2s_mc(sb + w_grp(j) + rank * 6400, &g_wop[hg][osrc_of(j) * 10 + rank * 5], 6400, fb, 3);
                }
                mbar_expect(BAR(res), 20480);
                if (layer) {
                    tma3d(sb + W_RES, TMAP(6), blk * 64, hg * 80, 0, BAR(res));
                } else {
#pragma unroll 1
                    for (int p = 0; p < 2; p++) {
                        tma3d(sb + W_RES + p * 10240, TMAP(10), hg * 80, blk * 64, p, BAR(res));
                        tma3d(sb + W_RES + p * 10240 + 8192, TMAP(5), hg * 80 + 64, blk * 64, p, BAR(res));
                    }
                }
            }
            __syncwarp();
        } else {
            const int ht = tid - 288, hw = warp - 9, mi = lane >> 3, mj = lane & 7, g = lane >> 2, q = lane & 3;
            auto F = [](uint32_t x) { return __uint_as_float(x); };
            auto U = [](float x) { return __float_as_uint(x); };
            const uint32_t lb = layer ^ 1, eb = ~EPOCH & 1u;
            if (layer && hw < 2) {
                const bf16* pp = g_x2T + (size_t)(chunk(hw, Q_SP) * 64 + lane) * XP + 1024 + 64 * blk + (lane & 6);
                const uint32_t a = sb + hw * Q_SB + g * 128 + (((2 * q) ^ g) << 4) + 2 * (g & 6);
                mbar_wait(BAR(fdone) - sizeof(Bars), 0);
                uint32_t bad;
                int spin = 0;
                do {
                    uint32_t v0, v1;
                    asm volatile("ld.relaxed.gpu.global.u32 %0, [%1];" : "=r"(v0) : "l"(pp) : "memory");
                    asm volatile("ld.relaxed.gpu.global.u32 %0, [%1];" : "=r"(v1) : "l"(pp + 32 * XP) : "memory");
                    bad = (v0 ^ eb) | (v1 ^ eb);
                } while (__any_sync(~0u, bad & 1u) && ++spin < (1 << 18));
                fence_async_global();
                TS(1);
                spin = 0;
                do {
                    if (elect_one()) {
                        mbar_expect(BAR(xland) + 8 * hw, Q_AB);
                        tma3d(sb + hw * Q_SB, TMAP(2), blk * 64, chunk(hw, Q_SP) * 64, 0, BAR(xland) + 8 * hw);
                    }
                    __syncwarp();
                    mbar_wait(BAR(xland) + 8 * hw, spin & 1);
                    bad = 0;
#pragma unroll
                    for (int i = 0; i < 16; i++) bad |= lds32(a + i * 1024) ^ eb;
                } while (__any_sync(~0u, bad & 1u) && ++spin < (1 << 16));
                if (lane == 0) mbar_expect(BAR(full) + 8 * hw, Q_BB);
                TS(9);
            }
            mbar_wait(BAR(full) + 8 * Q_SP * layer, 0);
            mbar_wait(BAR(full) + 8 * Q_SP * layer + 8, 0);
            if (ht == 0) TSX(2, 2);
            uint32_t xf[3][20];
#pragma unroll
            for (int i = 0; i < 3; i++) {
                const int tile = min(hw + 3 * i, 7);
#pragma unroll
                for (int k = 0; k < 5; k++) {
                    const int ch = c0 + 16 * k + 8 * (mi >> 1), tok = 16 * (tile & 3) + 8 * (mi & 1);
                    const uint32_t a = sb + ((ch >> 6) + Q_SP * layer) * Q_SB + (tile >> 2) * 8192;
                    if (layer == 0) ldsm_x4(xf[i][4 * k], xf[i][4 * k + 1], xf[i][4 * k + 2], xf[i][4 * k + 3], a + (tok + mj) * 128 + ((((ch & 63) >> 3) ^ mj) << 4));
                    else ldsm_x4_t(xf[i][4 * k], xf[i][4 * k + 1], xf[i][4 * k + 2], xf[i][4 * k + 3], a + ((ch & 63) + mj) * 128 + (((tok >> 3) ^ mj) << 4));
                }
            }
            fence_async_smem();
            __syncwarp();
            if (lane == 0) { mbar_arrive_cta(BAR(hdone), 0); mbar_arrive_cta(BAR(hdone), 1); }
            if (ht == 0) TSX(2, 3);
            if (layer == 0) {
                if (hw == 2 && elect_one()) { bulk_wait(); fence_async_global(); grid_arrive(g_bar[3][hg]); }
                __syncwarp();
                mbar_wait(BAR(kfree), 0);
            }
            if (ht == 0) TSX(2, 8);
#pragma unroll 1
            for (int tile = hw; tile < 8; tile += 3) {
                float a[4] = {0.f, 0.f, 0.f, 0.f};
#pragma unroll
                for (int j = 0; j < 20; j++) {
                    const float lo = bf_lo(xf[0][j]), hi = bf_hi(xf[0][j]);
                    a[2 * (j & 1)] += lo + hi; a[2 * (j & 1) + 1] = fmaf(lo, lo, fmaf(hi, hi, a[2 * (j & 1) + 1]));
                    xf[0][j] = xf[1][j]; xf[1][j] = xf[2][j];
                }
#pragma unroll
                for (int j = 0; j < 4; j++) { a[j] += __shfl_xor_sync(~0u, a[j], 1); a[j] += __shfl_xor_sync(~0u, a[j], 2); }
                if (q == 0) st_ll4(&g_stp[blk][hg][8 * tile + g], (U(a[0]) & ~1u) | lb, U(a[1]), U(a[2]), U(a[3]));
            }
            if (ht == 0) TSX(2, 4);
            if (layer == 0) {
                float t[4] = {0.f, 0.f, 0.f, 0.f};
                uint4 v[16];
                int spin = 0;
                uint32_t bad;
                do {
                    bad = 0;
#pragma unroll
                    for (int j = 0; j < 16; j++) v[j] = ld_ll4(&g_csp[hg][j][ht]);
#pragma unroll
                    for (int j = 0; j < 16; j++) bad |= v[j].x ^ eb;
                } while ((bad & 1u) && ++spin < (1 << 18));
#pragma unroll
                for (int j = 0; j < 16; j++) { t[0] += F(v[j].y); t[1] += F(v[j].z); t[2] += F(v[j].w); }
#pragma unroll
                for (int j = 0; j < 3; j++) if (q + 4 * j < 10) sts32(MISC(cs) + 4 * (80 * hw + 20 * (g >> 1) + 2 * (q + 4 * j) + (g & 1)), U(t[j]));
                if (hw == 2) grid_wait(g_bar[3][0], 8, 16 * (EPOCH + 1), lane);
            }
            if (ht == 0) TSX(2, 15);
            if (ht < 80) {
                const bool halo = ht >= 64;
                const int p = halo ? (ht >> 3) & 1 : ht >> 5, i = halo ? (ht & 7) - 8 : 8 + 2 * (ht & 24) + (ht & 7);
                const uint4* src = &g_stp[halo && blk ? blk - 1 : blk][0][halo ? 32 * p + 24 + (ht & 7) : ht];
                uint4 v[8];
                int spin = 0;
                uint32_t bad;
                do {
                    bad = 0;
#pragma unroll
                    for (int j = 0; j < 8; j++) v[j] = ld_ll4(src + 64 * j);
#pragma unroll
                    for (int j = 0; j < 8; j++) bad |= v[j].x ^ lb;
                } while ((bad & 1u) && ++spin < (1 << 18));
                float t[4] = {0.f, 0.f, 0.f, 0.f};
#pragma unroll
                for (int j = 0; j < 8; j++) { t[0] += F(v[j].x); t[1] += F(v[j].y); t[2] += F(v[j].z); t[3] += F(v[j].w); }
                const uint32_t s0 = ln_finish_packed(t[0], t[1]), s1 = ln_finish_packed(t[2], t[3]);
                const uint32_t am = MISC(mean) + 4 * (64 * p + i), ar = MISC(rstd) + 4 * (72 * p + i);
                if (!halo) { sts32(am - 32, U(bf_hi(s0))); sts32(am, U(bf_hi(s1))); sts32(ar, U(frcp(bf_lo(s0)))); }
                sts32(ar + 32, U(frcp(bf_lo(s1))));
            }
            fence_acquire();
            mbar_arrive(BAR(prep));
            if (ht == 0) TSX(2, 5);
        }
        __syncwarp();
        indices();
        {
            const uint4 ko[2] = {ldg_tab(16, tid & 127), ldg_tab(17, tid & 127)};
            conv_tables();
            kernel_stage<1>(ko, sb + Q_KDUMP + 4 * KG_RES, MISC(kg), 4, sb + F_EO + 2 * 8192, warp & 3, lane);
            fence_async_smem();
        }
        {
            const int p = warp & 1;
            const uint32_t fb = EPOCH ^ layer ^ 1, ob = MISC(ob) + 32 * p;
            auto fetch = [&](int j) {
                if (elect_one()) {
                    mbar_expect(ob + 8 * ((j - 1) & 3), 10240);
                    bulk_g2s(sb + o_slot(p, (j - 1) & 3), &g_of[osrc_of(j)][blk][640 * p], 10240, ob + 8 * ((j - 1) & 3));
                }
                __syncwarp();
            };
            if (warp < 10) {
                const uint32_t* pp = &g_of[osrc_of(1 + min(lane >> 2, 6))][blk][640 * p + 8 * (73 + 2 * (lane & 3)) + 7].x;
                mbar_wait(BAR(qdone), 0);
                mbar_wait(BAR(att) + 8 * p, 0);
                uint32_t miss = ~0u;
                int spin = 0;
#pragma unroll 1
                for (int j = 1; j < 8; j++) {
                    while (((miss >> (4 * j - 4)) & 15u) && ++spin < (1 << 18)) {
                        uint32_t v;
                        asm volatile("ld.relaxed.gpu.global.u32 %0, [%1];" : "=r"(v) : "l"(pp) : "memory");
                        miss = __ballot_sync(~0u, (v ^ fb) & 1u);
                        fence_async_global();
                    }
                    if (j == 1) TS(16);
                    if (j > 3) mbar_wait(ob + 128 + 8 * ((j - 1) & 3), layer);
                    fetch(j);
                }
                TS(17);
            } else {
#pragma unroll 1
                for (int j = 1, spin = 0; j < 8;) {
                    const int s = (j - 1) & 3;
                    mbar_wait(ob + 8 * s, (ophase >> s) & 1);
                    ophase ^= 1u << s;
                    const uint32_t a = sb + o_slot(p, s) + (lane >> 2) * 132 + (lane & 3) * 32;
                    uint32_t bad = 0;
#pragma unroll
                    for (int i = 0; i < 10; i++) bad |= lds32(a + i * 1024) ^ fb;
                    if (__any_sync(~0u, bad & 1u) && ++spin < (1 << 16)) { fetch(j); continue; }
                    if (lane == 0) mbar_arrive(ob + 64 + 8 * s);
                    j++;
                }
            }
        }
        TS_PHASE(2 * layer + 1);
        TS(0);
        indices();
        named_bar(3, 128);
        conv_wg<1>(5 * bx + 4, layer, sb + F_EO + 2 * 8192, sb + 2 * Q_SB, sb + F_S23, MISC(kg.kexp) + 16, MISC(epoch), sb + 3 * Q_SB, BAR(st), warp, lane, fa1, ftw,
        [&] {
            if (warp == 9) {
                auto F = [](uint32_t x) { return __uint_as_float(x); };
                mbar_wait(BAR(soon) + 8 * (hg >> 2), 0);
                TS(23);
                const uint4* src = &g_sp2[blk][hg][0][0] + lane;
                uint4* dst = (uint4*)(g_fs[(lane >> 2) & 1] + 1024 * (hg >> 2) + 64 * blk + 16 * (hg & 3)) + (lane & 3);
                const bool up = lane & 8;
#pragma unroll 1
                for (int spin = 0; spin < (1 << 18); spin++) {
                    const uint4 a = ld_ll4(src), b = ld_ll4(src + 32);
                    const bool ok = !__any_sync(~0u, ~((a.x ^ layer) & (b.x ^ layer)) & 1u);
                    const float s0 = F(a.x) + F(b.x), q0 = F(a.y) + F(b.y), s1 = F(a.z) + F(b.z), q1 = F(a.w) + F(b.w);
                    float sm = (up ? s1 : s0) + __shfl_xor_sync(~0u, up ? s0 : s1, 8), sq = (up ? q1 : q0) + __shfl_xor_sync(~0u, up ? q0 : q1, 8);
                    sm += __shfl_xor_sync(~0u, sm, 16); sq += __shfl_xor_sync(~0u, sq, 16);
                    const float m = sm * (1.0f / DM), r = frsq(fmaxf(fmaf(sq, 1.0f / DM, fmaf(-m, m, 1e-5f)), 1e-5f));
                    const uint32_t v = __float_as_uint(lane & 16 ? -m * r : r);
                    const uint32_t v0 = __shfl_sync(~0u, v, 4 * lane), v1 = __shfl_sync(~0u, v, 4 * lane + 1), v2 = __shfl_sync(~0u, v, 4 * lane + 2), v3 = __shfl_sync(~0u, v, 4 * lane + 3);
                    if (ok && lane < 8) st_ll4(dst, (v0 & ~1u) | (layer ^ 1), v1, v2, v3);
                    if (ok) break;
                }
            }
            TS(25);
            mbar_wait(BAR(staged), 0);
        }, [&] { mbar_wait(BAR(ardy), 0); }, [&] {
            if (tid == 352) prefetch_tmap(layer ? TMAP(9) : TMAP(2));
        } TS_PASS);
        conv_done();
    }
    } else {
#pragma unroll 1
    for (; layer < 2; layer++, bars += sizeof(Bars)) {
    indices();
    TS_PHASE(2 * layer);
    const int wg = warp >> 2, w = warp & 3;
    const int mi = lane >> 3, mj = lane & 7, g = lane >> 2, q = lane & 3;
    TS(2);
    float acc[120];
#pragma unroll
    for (int i = 0; i < 120; i++) acc[i] = 0.f;
    auto release = [&](int it) {
        if (lane == 0) { mbar_arrive_cta(BAR(empty) + 8 * (it & (Q_ST - 1)), 0); mbar_arrive_cta(BAR(empty) + 8 * (it & (Q_ST - 1)), 1); }
    };
#pragma unroll 1
    for (int it = 0; it < 10; it++) {
        const int s = it & (Q_ST - 1);
        const uint32_t st = sb + s * Q_SB;
        const bool hold = wg == 1 && it == Q_S0;
        if (hold) {
            wg_wait<0>();
            release(it - 1);
            mbar_wait(BAR(go), 0);
        }
        mbar_wait(BAR(full) + 8 * (s), (it >> 2) & 1);
        if (it < 2) TS(3 + it);
        if (it == 6) TS(5);
        if (it == 9) TS(6);
        const uint64_t da = mkdesc(st + wg * 8192, 16, 1024, 1);
        const uint64_t db = mkdesc(st + Q_AB, 4096, 1024, 1);
        const uint64_t dr = mkdesc(st + Q_AB + 12288, 1024, 256, 3);
        if (layer == 0) {
            wg_fence();
#pragma unroll
            for (int ks = 0; ks < 4; ks++) {
                const int sc = 1;
                wgmma_n192<0, 1>(*(float(*)[96]) & acc[0], da + ks * 2, db + (ks >> 1) * 960 + (ks & 1) * 128, sc);
                wgmma_n48<0, 1>(*(float(*)[24]) & acc[96], da + ks * 2, dr + (ks >> 1) * 960 + (ks & 1) * 32, sc);
            }
            wg_commit();
        } else {
            wg_fence();
#pragma unroll
            for (int ks = 0; ks < 4; ks++) {
                const int sc = 1;
                wgmma_n192<1, 1>(*(float(*)[96]) & acc[0], da + ks * 128, db + (ks >> 1) * 960 + (ks & 1) * 128, sc);
                wgmma_n48<1, 1>(*(float(*)[24]) & acc[96], da + ks * 128, dr + (ks >> 1) * 960 + (ks & 1) * 32, sc);
            }
            wg_commit();
        }
        wg_wait<1>();
        if (it > 0 && !hold) release(it - 1);
    }
    if (wg == 0 && lane == 0) mbar_arrive(BAR(go));
    asm volatile("setmaxnreg.inc.sync.aligned.u32 %0;" ::"n"(R_CONS));
    mbar_wait(BAR(prep), 0);
    const uint32_t ob = layer ^ 1;
    const bool first = (blk == 0 && w == 0);
    const bool sel0 = (2 * q > g), sel1 = (2 * q + 1 > g);
    constexpr float SC = 0.22360679774997896f * 1.4426950408889634f;
    const float m0 = __uint_as_float(lds32(MISC(mean) + 4 * (16 * warp + g))), m1 = __uint_as_float(lds32(MISC(mean) + 4 * (16 * warp + g + 8)));
    uint4 cs[3][5];
    auto cs_load = [&](int p) {
#pragma unroll
        for (int i = 0; i < 5; i++) cs[p][i] = lds128(MISC(cs) + 4 * (80 * p + 20 * q + 4 * i));
    };
    cs_load(1); cs_load(2);
    wg_wait<0>();
    TS(7);
    if (lane == 0) mbar_arrive(BAR(qdone));
    uint32_t ql[10], qh[10], kl[10], kh[10], vl[10], vh[10];
    auto fold = [&](int p, int f, int h) {
        const int j = (f < 8) ? 8 * p + f : 24 + 2 * p + (f - 8);
        const float c0 = __uint_as_float(u4(cs[p][f >> 1], 2 * (f & 1))), c1 = __uint_as_float(u4(cs[p][f >> 1], 2 * (f & 1) + 1));
        const float m = h ? m1 : m0;
        return pack2(fmaf(-m, c0, acc[4 * j + 2 * h]), fmaf(-m, c1, acc[4 * j + 2 * h + 1]));
    };
#pragma unroll
    for (int f = 0; f < 10; f++) { vh[f] = fold(2, f, 1); if (f < A_VLO) vl[f] = fold(2, f, 0); }
#pragma unroll
    for (int f = 0; f < 10; f++) kh[f] = fold(1, f, 1);
#pragma unroll
    for (int f = 0; f < A_VLO; f++) asm volatile("" : "+r"(vl[f]));
    {
        const uint32_t mk = w == 3 ? 1u : 0u;
        auto mark = [&](uint32_t& v) { v = (v & ~mk) | (ob & mk); };
        mark(kh[0]); mark(kh[5]); mark(vh[0]); mark(vh[4]); mark(vh[8]);
    }
    if (w == 3) {
        uint4* hp = &g_halo[bx][wg][0][lane];
        st_ll4(hp, kh[0], kh[1], kh[3], kh[4]); st_ll4(hp + 32, kh[5], kh[6], kh[8], kh[9]);
        st_ll4(hp + 64, vh[0], vh[1], vh[2], vh[3]); st_ll4(hp + 96, vh[4], vh[5], vh[6], vh[7]);
        st_ll4(hp + 128, vh[8], vh[9], kh[2], kh[7]);
    } else {
        const uint32_t a = sb + Q_EOFF + wg * 8192 + w * Q_ESLOT + mj * Q_EROW + mi * 16;
        stsm_x4(a, kh[0], kh[1], kh[3], kh[4]);
        stsm_x4(a + 64, kh[5], kh[6], kh[8], kh[9]);
        stsm_x4(a + 128, vh[0], vh[1], vh[2], vh[3]);
        stsm_x4(a + 192, vh[4], vh[5], vh[6], vh[7]);
        stsm_x4(a + 256, vh[8], vh[9], kh[2], kh[7]);
        __syncwarp();
        if (lane == 0) mbar_arrive(BAR(ex) + 8 * warp);
    }
    TS(9);
    cs_load(0);
#pragma unroll
    for (int f = 0; f < 10; f++) { kl[f] = fold(1, f, 0); if (f >= A_VLO) vl[f] = fold(2, f, 0); }
#pragma unroll
    for (int f = 0; f < 10; f++) { ql[f] = fold(0, f, 0); qh[f] = fold(0, f, 1); }
    auto rs = [&](int i) { return __uint_as_float(lds32(MISC(rstd) + 4 * (72 * wg + 16 * w + i))); };
    const float kx0 = rs(2 * q + (sel0 ? 0 : 8)), kx1 = rs(2 * q + (sel1 ? 1 : 9)), ky0 = rs(2 * q + (sel0 ? 8 : 16)), ky1 = rs(2 * q + (sel1 ? 9 : 17));
    const float rx = SC * rs(8 + g), ry = SC * rs(16 + g), cx0 = rx * kx0, cx1 = rx * kx1, cy0 = ry * ky0, cy1 = ry * ky1;
    uint4 hv[5];
    const uint4* hp = &g_halo[bx - 1][wg][0][lane];
    auto prev = [&] {
        if (w > 0) {
            const uint32_t a = sb + Q_EOFF + wg * 8192 + (w - 1) * Q_ESLOT + mj * Q_EROW + mi * 16;
            mbar_wait(BAR(ex) + 8 * (warp - 1), 0);
            ldsm_x4(hv[0].x, hv[0].y, hv[0].z, hv[0].w, a);
            ldsm_x4(hv[1].x, hv[1].y, hv[1].z, hv[1].w, a + 64);
            ldsm_x4_t(hv[2].x, hv[2].y, hv[2].z, hv[2].w, a + 128);
            ldsm_x4_t(hv[3].x, hv[3].y, hv[3].z, hv[3].w, a + 192);
            ldsm_x2_t(hv[4].x, hv[4].y, a + 256);
            ldsm_x2(hv[4].z, hv[4].w, a + 288 - (lane >> 4) * 32);
        } else if (blk > 0) {
#pragma unroll
            for (int f = 0; f < 5; f++) hv[f] = ld_ll4(hp + 32 * f);
        } else {
#pragma unroll
            for (int f = 0; f < 5; f++) hv[f] = make_uint4(0, 0, 0, 0);
        }
    };
    uint32_t vt[10][2];
#pragma unroll
    for (int f = 0; f < 10; f++) { vt[f][0] = movm_t(vl[f]); vt[f][1] = movm_t(vh[f]); }
    prev();
    TS(10);
    auto FA = [](int h) { return h == 0 ? 0 : h == 1 ? 3 : h == 2 ? 5 : 8; };
    auto FH = [](int h) { return h < 2 ? 2 : 7; };
    const uint32_t pm = (sel0 ? 0xFFFFu : 0u) | (sel1 ? 0xFFFF0000u : 0u);
    auto softmax = [&](float x0, float x1, float k0, float k1) {
        float mx = fmaxf(x0, x1);
        mx = fmaxf(mx, __shfl_xor_sync(~0u, mx, 1));
        mx = fmaxf(mx, __shfl_xor_sync(~0u, mx, 2));
        x0 = ex2(x0 - mx); x1 = ex2(x1 - mx);
        float sx = x0 + x1;
        sx += __shfl_xor_sync(~0u, sx, 1);
        sx += __shfl_xor_sync(~0u, sx, 2);
        const float ix = frcp(sx);
        return pack2(x0 * k0 * ix, x1 * k1 * ix);
    };
    uint32_t qm[4][2], py[4];
    float sl[4][2];
#pragma unroll
    for (int h = 0; h < 4; h++) {
        const int fa = FA(h), fb = fa + 1, fh = FH(h);
        const bool mine = (h & 1) ? (q >= 2) : (q < 2);
        qm[h][0] = mine ? ql[fh] : 0u; qm[h][1] = mine ? qh[fh] : 0u;
        float S1[4] = {0.f, 0.f, 0.f, 0.f}, S2[4] = {0.f, 0.f, 0.f, 0.f};
        mma16816(S1, ql[fa], qh[fa], ql[fb], qh[fb], kl[fa], kl[fb]); mma1688(S1, qm[h][0], qm[h][1], kl[fh]);
        mma16816(S2, ql[fa], qh[fa], ql[fb], qh[fb], kh[fa], kh[fb]); mma1688(S2, qm[h][0], qm[h][1], kh[fh]);
        sl[h][0] = S1[0]; sl[h][1] = S1[1];
        py[h] = softmax((sel0 ? S1[2] : S2[2]) * cy0, (sel1 ? S1[3] : S2[3]) * cy1, ky0, ky1);
    }
    TS(11);
    if (w == 0 && blk > 0) {
        ll_check5(hv, hp, ob);
#pragma unroll
        for (int f = 2; f < 4; f++) hv[f] = make_uint4(movm_t(hv[f].x), movm_t(hv[f].y), movm_t(hv[f].z), movm_t(hv[f].w));
        hv[4].x = movm_t(hv[4].x); hv[4].y = movm_t(hv[4].y);
    }
    const uint32_t kp[10] = {hv[0].x, hv[0].y, hv[4].z, hv[0].z, hv[0].w, hv[1].x, hv[1].y, hv[4].w, hv[1].z, hv[1].w};
    const uint32_t vp[10] = {hv[2].x, hv[2].y, hv[2].z, hv[2].w, hv[3].x, hv[3].y, hv[3].z, hv[3].w, hv[4].x, hv[4].y};
    TS(12);
    const uint4 ko[2] = {ldg_tab(16, tid & 127), ldg_tab(17, tid & 127)};
    const float bx0 = first && sel0 ? -INFINITY : 0.f, bx1 = first && sel1 ? -INFINITY : 0.f;
    float oacc[10][4];
#pragma unroll
    for (int h = 0; h < 4; h++) {
        const int fa = FA(h), fb = fa + 1, fh = FH(h);
        const bool mine = (h & 1) ? (q >= 2) : (q < 2);
        float S0[4] = {0.f, 0.f, 0.f, 0.f};
        mma16816(S0, ql[fa], qh[fa], ql[fb], qh[fb], kp[fa], kp[fb]); mma1688(S0, qm[h][0], qm[h][1], kp[fh]);
        const uint32_t px = softmax(fmaf(sel0 ? S0[0] : sl[h][0], cx0, bx0), fmaf(sel1 ? S0[1] : sl[h][1], cx1, bx1), kx0, kx1);
#pragma unroll
        for (int i = 0; i < 3; i++) {
            const int f = (i == 0) ? fa : (i == 1) ? fb : fh;
            float O[4] = {0.f, 0.f, 0.f, 0.f};
            mma16816(O, px & ~pm, py[h] & pm, 0u, py[h] & ~pm, vt[f][0], vt[f][1]);
            mma1688(O, px & pm, 0u, vp[f]);
            if (i < 2 || !(h & 1) || mine) { oacc[f][0] = O[0]; oacc[f][1] = O[1]; oacc[f][2] = O[2]; oacc[f][3] = O[3]; }
        }
    }
    TS(13);
    float aw[40];
    uint4 of[5];
    {
        const uint32_t fb = EPOCH ^ ob, mk[2] = {q == 0 || mj == 2 * w, q == 0 || mj == 2 * w + 1};
        uint32_t* dst = &g_of[hg][blk][640 * wg + 16 * w].x + lane;
#pragma unroll
        for (int i = 0; i < 20; i++) {
            const uint32_t v = (pack2(oacc[i >> 1][2 * (i & 1)], oacc[i >> 1][2 * (i & 1) + 1]) & ~mk[i & 1]) | (fb & mk[i & 1]);
            u4r(of[i >> 2], i & 3) = v;
            asm volatile("st.relaxed.gpu.global.u32 [%0], %1;" ::"l"(dst + 256 * (i >> 1) + 32 * (i & 1)), "r"(v) : "memory");
        }
        if (lane == 0) mbar_arrive(BAR(att) + 8 * wg);
        TS(14);
    }
    const uint32_t obar = MISC(ob) + 32 * wg;
    named_bar(1 + wg, 128);
    kernel_stage<2>(ko, sb + Q_KDUMP + 2 * wg * KG_RES, MISC(kg), 2 * wg, sb + F_EO + wg * 8192, w, lane);
    TS(15);
    uint32_t res[20];
    mbar_wait(BAR(res), 0);
    const uint32_t ta = (8 * (mi >> 1) + mj) * 128 + (((2 * w + (mi & 1)) ^ mj) << 4);
    if (layer == 0) {
        const int tok = 16 * w + 8 * (mi & 1) + mj;
#pragma unroll
        for (int k = 0; k < 4; k++)
            ldsm_x4(res[4 * k], res[4 * k + 1], res[4 * k + 2], res[4 * k + 3], sb + W_RES + wg * 10240 + tok * 128 + (((2 * k + (mi >> 1)) ^ mj) << 4));
        ldsm_x4(res[16], res[17], res[18], res[19], sb + W_RES + wg * 10240 + 8192 + tok * 32 + (((mi >> 1) ^ (mj >> 2)) << 4));
    } else {
#pragma unroll
        for (int k = 0; k < 5; k++) ldsm_x4_t(res[4 * k], res[4 * k + 1], res[4 * k + 2], res[4 * k + 3], sb + W_RES + wg * 10240 + k * 2048 + ta);
    }
    fence_async_smem();
    __syncwarp();
    if (lane == 0) mbar_arrive(obar + 128 + 24);
    {
#pragma unroll
        for (int i = 0; i < 20; i++) { aw[2 * i] = bf_lo(res[i]); aw[2 * i + 1] = bf_hi(res[i]); }
        mbar_wait(BAR(wfull), 0);
        const uint64_t dm = mkdesc(sb + w_grp(0), 1280, 128, 0);
        wg_fence();
#pragma unroll
        for (int k = 0; k < 5; k++) wgmma_rs80(aw, of[k], dm + k * 160, 1);
        wg_commit();
    }
    conv_tables();
    wg_wait<0>();
    TS(8);
#pragma unroll 1
    for (int j = 1; j < 8; j++) {
        const int s = (j - 1) & 3;
        const uint64_t da = mkdesc(sb + o_slot(wg, s), 1024, 128, 0), dm = mkdesc(sb + w_grp(j), 1280, 128, 0);
        if (s == 2) mbar_wait(BAR(wfull) + 2 * (j + 1), 0);
        mbar_wait(obar + 64 + 8 * s, s == 3 ? layer : j > 4);
        if (j == 1) TS(17);
        if (j == 5) TS(18);
        wg_fence();
#pragma unroll
        for (int k = 0; k < 5; k++) wgmma_ss80(aw, da + k * 128, dm + k * 160);
        wg_commit();
        wg_wait<1>();
        if (j > 1 && j < 5 && lane == 0) mbar_arrive(obar + 128 + 8 * (j - 2));
    }
    if (lane == 0) mbar_arrive(BAR(soon) + 8 * wg);
    named_bar(1 + wg, 128);
    wg_wait<0>();
    TS(19);
    {
        float a[2][4] = {{0.f, 0.f, 0.f, 0.f}, {0.f, 0.f, 0.f, 0.f}};
#pragma unroll
        for (int i = 0; i < 40; i++) { a[i & 1][i & 2] += aw[i]; a[i & 1][(i & 2) + 1] = fmaf(aw[i], aw[i], a[i & 1][(i & 2) + 1]); }
#pragma unroll
        for (int j = 0; j < 4; j++) { a[0][j] += a[1][j]; a[0][j] += __shfl_xor_sync(~0u, a[0][j], 1); a[0][j] += __shfl_xor_sync(~0u, a[0][j], 2); }
        if (q == 0) st_ll4(&g_sp2[blk][warp][hg][g], (__float_as_uint(a[0][0]) & ~1u) | ob, __float_as_uint(a[0][1]), __float_as_uint(a[0][2]), __float_as_uint(a[0][3]));
    }
    TS(23);
#pragma unroll
    for (int i = 0; i < 20; i++) res[i] = pack2(aw[2 * i], aw[2 * i + 1]);
    {
        const uint32_t mk = (g & 3) ? 0u : 0x00010001u;
#pragma unroll
        for (int k = 0; k < 5; k++) {
            uint32_t m[4];
#pragma unroll
            for (int i = 0; i < 4; i++) m[i] = (res[4 * k + i] & ~mk) | (mk & (0u - ob));
            stsm_x4_t(sb + w_out(wg) + k * 2048 + ta, m[0], m[1], m[2], m[3]);
        }
        fence_async_smem();
        named_bar(1 + wg, 128);
        if (w == 0 && elect_one()) {
            asm volatile("cp.async.bulk.tensor.2d.global.shared::cta.bulk_group [%0, {%2, %3}], [%1];"
                         ::"l"(TMAP(7)), "r"(sb + w_out(wg)), "r"(1024 * wg + 64 * blk), "r"(hg * 80) : "memory");
            bulk_commit();
            mbar_arrive(BAR(staged));
        }
        __syncwarp();
        TS(20);
    }
    if (layer) {
#pragma unroll
        for (int k = 0; k < 5; k++) stsm_x4_t(sb + W_RES + wg * 10240 + k * 2048 + ta, res[4 * k], res[4 * k + 1], res[4 * k + 2], res[4 * k + 3]);
    }
    TS(22);
    TS_PHASE(2 * layer + 1);
    TS(0);
    indices();
    conv_wg<2>(5 * bx + 2 * (warp >> 2), layer, sb + F_EO + (warp >> 2) * 8192, sb + (warp >> 2) * Q_SB, sb + F_S23, MISC(kg.kexp) + 8 * (warp >> 2),
               MISC(epoch), sb + 3 * Q_SB, BAR(st), warp, lane, fa1, ftw, [&] {
        if ((warp & 3) == 0 && elect_one()) {
            asm volatile("cp.async.bulk.wait_group.read 0;" ::: "memory");
            if (layer == 0) { mbar_arrive_cta(BAR(wfree), 0); mbar_arrive_cta(BAR(wfree), 1); }
        }
        __syncwarp();
    }, [&] {
        if (warp == 0) {
            const bf16* pp = g_x1T + (size_t)(5 * bx + 4) * XP + 64 * lane + 60;
            mbar_wait(BAR(staged), 0);
            uint32_t v;
            int spin = 0;
            do { asm volatile("ld.relaxed.gpu.global.u32 %0, [%1];" : "=r"(v) : "l"(pp) : "memory"); } while (__any_sync(~0u, ~(v ^ layer) & 1u) && ++spin < (1 << 18));
            if (lane == 0) mbar_arrive(BAR(ardy));
        } else {
            mbar_wait(BAR(ardy), 0);
        }
    }, [&] {
        if (layer == 0 && warp >= 4 && elect_one()) { mbar_wait(BAR(wfree), 0); issue_w(BAR(full) + sizeof(Bars), warp - 4, 1); }
        __syncwarp();
    } TS_PASS);
    conv_done();
    asm volatile("setmaxnreg.dec.sync.aligned.u32 168;");
    }
    named_bar(1 + (warp >> 2), 128);
    asm volatile("setmaxnreg.dec.sync.aligned.u32 %0;" ::"n"(504 - 2 * R_CONS));
    }
    indices();
    const int cq = 4 * (warp >> 1) + (lane & 3), tg = 8 * (warp & 1) + (lane >> 2);
    const uint32_t fb = ~EPOCH & 1u;
    uint2 xr[4][2];
    __syncthreads();
    if (tid < 320) {
#pragma unroll
        for (int i = 0; i < 8; i++) {
            const int ch = 4 * cq + (i >> 1);
            asm volatile("ld.shared.v2.u32 {%0, %1}, [%2];" : "=r"(xr[i >> 1][i & 1].x), "=r"(xr[i >> 1][i & 1].y)
                         : "r"(sb + W_RES + (i & 1) * 10240 + ch * 128 + (((tg >> 1) ^ (ch & 7)) << 4) + (tg & 1) * 8) : "memory");
        }
    }
    if (tid < 320) {
        const uint4* src = &g_of[hg][blk][64 * cq + tg];
        uint4 v[4];
#pragma unroll
        for (int i = 0; i < 4; i++) v[i] = make_uint4(~fb, 0, 0, 0);
        int spin = 0;
        while (true) {
#pragma unroll
            for (int i = 0; i < 4; i++) if ((v[i].x ^ fb) & 1u) v[i] = ld_ll4(src + 16 * i);
            if (!(((v[0].x ^ fb) | (v[1].x ^ fb) | (v[2].x ^ fb) | (v[3].x ^ fb)) & 1u) || ++spin >= (1 << 18)) break;
        }
        TS(21);
#pragma unroll
        for (int i = 0; i < 16; i++) asm("add.rn.bf16x2 %0, %0, %1;" : "+r"(u4r(v[i >> 2], i & 3)) : "r"((i & 1) ? xr[i >> 2][(i >> 1) & 1].y : xr[i >> 2][(i >> 1) & 1].x));
#pragma unroll
        for (int j = 0; j < 8; j++) {
            const uint32_t sel = (j & 2) ? 0x7632 : 0x5410;
            const int k = 2 * (j & 1) + (j >> 2);
            asm volatile("st.shared.v2.u32 [%0], {%1, %2};" ::"r"(sb + 2 * Q_SB + (16 * j + tg) * 160 + cq * 8),
                         "r"(__byte_perm(u4(v[0], k), u4(v[1], k), sel)), "r"(__byte_perm(u4(v[2], k), u4(v[3], k), sel)) : "memory");
        }
        fence_async_smem();
    }
    __syncthreads();
    if (warp == 0 && elect_one()) {
        asm volatile("cp.async.bulk.tensor.3d.global.shared::cta.bulk_group [%0, {%2, %3, 0}], [%1];" ::"l"(TMAP(9)), "r"(sb + 2 * Q_SB), "r"(80 * hg), "r"(16 * blk) : "memory");
        bulk_commit();
        asm volatile("cp.async.bulk.wait_group.read 0;" ::: "memory");
    }
    if (bx == 0 && tid == 0) g_epoch = (EPOCH + 1) & 0x3FFFFFFFu;
    TS(22);
    TS_END;
}
typedef CUresult (*EncodeTiledFn)(CUtensorMap*, CUtensorMapDataType, cuuint32_t, void*, const cuuint64_t*, const cuuint64_t*, const cuuint32_t*,
                                  const cuuint32_t*, CUtensorMapInterleave, CUtensorMapSwizzle, CUtensorMapL2promotion, CUtensorMapFloatOOBfill);

static void make_map(EncodeTiledFn enc, CUtensorMap* m, const void* base, int rank, const cuuint64_t* dims, const cuuint64_t* strides,
                     const cuuint32_t* box, CUtensorMapSwizzle sw) {
    cuuint32_t es[4] = {1, 1, 1, 1};
    enc(m, CU_TENSOR_MAP_DATA_TYPE_BFLOAT16, rank, (void*)base, dims, strides, box, es, CU_TENSOR_MAP_INTERLEAVE_NONE, sw,
        sw == CU_TENSOR_MAP_SWIZZLE_128B ? CU_TENSOR_MAP_L2_PROMOTION_L2_128B : CU_TENSOR_MAP_L2_PROMOTION_NONE, CU_TENSOR_MAP_FLOAT_OOB_FILL_NONE);
}

template <typename... KArgs, typename... Args>
static void launch(void (*kern)(KArgs...), int grid, int block, int smem, int cluster, bool pdl, Args... args) {
    cudaLaunchConfig_t cfg = {};
    cfg.gridDim = dim3(grid); cfg.blockDim = dim3(block); cfg.dynamicSmemBytes = smem; cfg.stream = cudaStreamPerThread;
    cudaLaunchAttribute at[2];
    int n = 0;
    if (cluster > 1) { at[n].id = cudaLaunchAttributeClusterDimension; at[n].val.clusterDim.x = cluster; at[n].val.clusterDim.y = 1; at[n].val.clusterDim.z = 1; n++; }
    if (pdl) { at[n].id = cudaLaunchAttributeProgrammaticStreamSerialization; at[n].val.programmaticStreamSerializationAllowed = 1; n++; }
    cfg.attrs = at; cfg.numAttrs = n;
    cudaLaunchKernelEx(&cfg, kern, KArgs(args)...);
}

struct HostState {
    bool ready = false;
    const void* key[4] = {nullptr, nullptr, nullptr, nullptr};
    CUtensorMap mX[2], mRes[2], mW, mWr, mWo, mOut, mFin, mResA;
    bf16 *x1T, *x2T;
    unsigned* epoch;
};

extern "C" void kernel_launch(void* const* d_in, const int* in_sizes, int n_in, void* d_out, int out_size) {
    const bf16* x = (const bf16*)d_in[0];
    const bf16* wqkv = (const bf16*)d_in[1];
    const bf16* wo = (const bf16*)d_in[2];
    const bf16* lar = (const bf16*)d_in[4];
    const bf16* aim = (const bf16*)d_in[5];
    const bf16* cre = (const bf16*)d_in[6];
    const bf16* cim = (const bf16*)d_in[7];
    const bf16* logdt = (const bf16*)d_in[8];
    const bf16* dskip = (const bf16*)d_in[9];
    static HostState hs;
    if (!hs.ready || hs.key[0] != wqkv || hs.key[1] != wo || hs.key[2] != x || hs.key[3] != d_out) {
        void* fn = nullptr;
        cudaDriverEntryPointQueryResult qr;
        cudaGetDriverEntryPoint("cuTensorMapEncodeTiled", &fn, cudaEnableDefault, &qr);
        EncodeTiledFn enc = (EncodeTiledFn)fn;
        cudaGetSymbolAddress((void**)&hs.epoch, g_epoch);
        cudaGetSymbolAddress((void**)&hs.x1T, g_x1T);
        cudaGetSymbolAddress((void**)&hs.x2T, g_x2T);
        {
            cuuint64_t d[3] = {DM, SEQ / 2, 2}, s[2] = {DM * 4, DM * 2};
            cuuint32_t b[3] = {64, 64, 2}, ba[3] = {64, 64, 1}, br[3] = {16, 64, 1};
            make_map(enc, &hs.mX[0], x, 3, d, s, b, CU_TENSOR_MAP_SWIZZLE_128B);
            make_map(enc, &hs.mResA, x, 3, d, s, ba, CU_TENSOR_MAP_SWIZZLE_128B);
            make_map(enc, &hs.mRes[0], x, 3, d, s, br, CU_TENSOR_MAP_SWIZZLE_32B);
            cuuint64_t d2[3] = {SEQ / 2, DM, 2}, s2[2] = {XP * 2, SEQ};
            cuuint32_t b2[3] = {64, 80, 2};
            make_map(enc, &hs.mX[1], hs.x2T, 3, d2, s2, b, CU_TENSOR_MAP_SWIZZLE_128B);
            make_map(enc, &hs.mRes[1], hs.x2T, 3, d2, s2, b2, CU_TENSOR_MAP_SWIZZLE_128B);
            cuuint64_t d3[2] = {SEQ, DM};
            make_map(enc, &hs.mOut, hs.x1T, 2, d3, s2, b2, CU_TENSOR_MAP_SWIZZLE_128B);
        }
        { cuuint64_t d[2] = {3 * DM, DM}, s[1] = {3 * DM * 2}; cuuint32_t b[2] = {64, 32};
          make_map(enc, &hs.mW, wqkv, 2, d, s, b, CU_TENSOR_MAP_SWIZZLE_128B); }
        { cuuint64_t d[3] = {DM, DM, 3}, s[2] = {3 * DM * 2, DM * 2}; cuuint32_t b[3] = {16, 32, 3};
          make_map(enc, &hs.mWr, wqkv, 3, d, s, b, CU_TENSOR_MAP_SWIZZLE_32B); }
        { cuuint64_t d[4] = {8, 8, DM / 8, DM / 8}, s[3] = {DM * 2, 16, DM * 16}; cuuint32_t b[4] = {8, 8, 10, 5};
          make_map(enc, &hs.mWo, wo, 4, d, s, b, CU_TENSOR_MAP_SWIZZLE_NONE); }
        { cuuint64_t d[3] = {DM, SEQ / 8, 8}, s[2] = {DM * 16, DM * 2}; cuuint32_t b[3] = {80, 16, 8};
          make_map(enc, &hs.mFin, d_out, 3, d, s, b, CU_TENSOR_MAP_SWIZZLE_NONE); }
        cudaFuncSetAttribute(fused_kernel, cudaFuncAttributeMaxDynamicSharedMemorySize, Q_SMEM);
        hs.key[0] = wqkv; hs.key[1] = wo; hs.key[2] = x; hs.key[3] = d_out;
        hs.ready = true;
    }
    const SsmParams sp = {lar, aim, cre, cim, logdt, dskip, hs.epoch};
    launch(fused_kernel, 128, 384, Q_SMEM, 2, false, sp, hs.mX[0], hs.mX[1], hs.mW, hs.mWr, hs.mRes[0], hs.mRes[1], hs.mOut, hs.mWo, hs.mFin, hs.mResA);
}
```

```cpp
#include <cuda_runtime.h>
#include <cuda.h>
#include <cuda_bf16.h>
#include <cuda_fp16.h>
#include <stdint.h>

typedef __nv_bfloat16 bf16;

constexpr int SEQ = 2048;
constexpr int DM  = 640;
constexpr int XP  = SEQ + 64;
constexpr int NMODE = 192;

__device__ __forceinline__ uint32_t s2u(const void* p) { return (uint32_t)__cvta_generic_to_shared(p); }
__device__ __forceinline__ void mbar_init(uint32_t b, int c) { asm volatile("mbarrier.init.shared::cta.b64 [%0], %1;" ::"r"(b), "r"(c)); }
__device__ __forceinline__ void mbar_expect(uint32_t b, uint32_t bytes) { asm volatile("mbarrier.arrive.expect_tx.shared::cta.b64 _, [%0], %1;" ::"r"(b), "r"(bytes) : "memory"); }
__device__ __forceinline__ void mbar_arrive(uint32_t b) { asm volatile("mbarrier.arrive.shared::cta.b64 _, [%0];" ::"r"(b) : "memory"); }
__device__ __forceinline__ void mbar_arrive_cta(uint32_t b, uint32_t cta) {
    asm volatile("{\n.reg .b32 ra;\nmapa.shared::cluster.u32 ra, %0, %1;\nmbarrier.arrive.shared::cluster.b64 _, [ra];\n}" ::"r"(b), "r"(cta) : "memory");
}
__device__ __forceinline__ void mbar_wait(uint32_t b, uint32_t ph) {
#ifdef M_SAFE
    asm volatile("{\n.reg .pred p;\n.reg .u32 n;\nmbarrier.try_wait.parity.shared::cta.b64 p, [%0], %1;\n@p bra D;\nmov.u32 n, 0;\n"
                 "W: mbarrier.try_wait.parity.shared::cta.b64 p, [%0], %1;\n@p bra D;\nadd.u32 n, n, 1;\nsetp.lt.u32 p, n, 4194304;\n@p bra W;\ntrap;\nD:\n}"
                 ::"r"(b), "r"(ph) : "memory");
#else
    asm volatile("{\n.reg .pred p;\nW: mbarrier.try_wait.parity.shared::cta.b64 p, [%0], %1;\n@!p bra W;\n}" ::"r"(b), "r"(ph) : "memory");
#endif
}
__device__ __forceinline__ void fence_mbar_init() { asm volatile("fence.mbarrier_init.release.cluster;" ::: "memory"); }
__device__ __forceinline__ void cluster_sync() { asm volatile("barrier.cluster.arrive.aligned;\nbarrier.cluster.wait.aligned;" ::: "memory"); }
__device__ __forceinline__ void pdl_wait() { asm volatile("griddepcontrol.wait;" ::: "memory"); }
__device__ __forceinline__ void pdl_launch() { asm volatile("griddepcontrol.launch_dependents;" ::: "memory"); }
__device__ __forceinline__ void named_bar(int id, int n) { asm volatile("bar.sync %0, %1;" ::"r"(id), "r"(n) : "memory"); }
__device__ __forceinline__ void fence_async_smem() { asm volatile("fence.proxy.async.shared::cta;" ::: "memory"); }

__device__ __forceinline__ void tma2d(uint32_t dst, const CUtensorMap* m, int c0, int c1, uint32_t bar) {
    asm volatile("cp.async.bulk.tensor.2d.shared::cluster.global.mbarrier::complete_tx::bytes [%0], [%1, {%3, %4}], [%2];"
                 ::"r"(dst), "l"(m), "r"(bar), "r"(c0), "r"(c1) : "memory");
}
__device__ __forceinline__ void tma2d_mc(uint32_t dst, const CUtensorMap* m, int c0, int c1, uint32_t bar, uint16_t mask) {
    asm volatile("cp.async.bulk.tensor.2d.shared::cluster.global.mbarrier::complete_tx::bytes.multicast::cluster [%0], [%1, {%3, %4}], [%2], %5;"
                 ::"r"(dst), "l"(m), "r"(bar), "r"(c0), "r"(c1), "h"(mask) : "memory");
}
__device__ __forceinline__ void tma3d(uint32_t dst, const CUtensorMap* m, int c0, int c1, int c2, uint32_t bar) {
    asm volatile("cp.async.bulk.tensor.3d.shared::cluster.global.mbarrier::complete_tx::bytes [%0], [%1, {%3, %4, %5}], [%2];"
                 ::"r"(dst), "l"(m), "r"(bar), "r"(c0), "r"(c1), "r"(c2) : "memory");
}
__device__ __forceinline__ void tma3d_mc(uint32_t dst, const CUtensorMap* m, int c0, int c1, int c2, uint32_t bar, uint16_t mask) {
    asm volatile("cp.async.bulk.tensor.3d.shared::cluster.global.mbarrier::complete_tx::bytes.multicast::cluster [%0], [%1, {%3, %4, %5}], [%2], %6;"
                 ::"r"(dst), "l"(m), "r"(bar), "r"(c0), "r"(c1), "r"(c2), "h"(mask) : "memory");
}
__device__ __forceinline__ void bulk_g2s(uint32_t dst, const void* src, uint32_t bytes, uint32_t bar) {
    asm volatile("cp.async.bulk.shared::cluster.global.mbarrier::complete_tx::bytes [%0], [%1], %2, [%3];"
                 ::"r"(dst), "l"(src), "r"(bytes), "r"(bar) : "memory");
}
__device__ __forceinline__ void bulk_g2s_mc(uint32_t dst, const void* src, uint32_t bytes, uint32_t bar, uint16_t mask) {
    asm volatile("cp.async.bulk.shared::cluster.global.mbarrier::complete_tx::bytes.multicast::cluster [%0], [%1], %2, [%3], %4;"
                 ::"r"(dst), "l"(src), "r"(bytes), "r"(bar), "h"(mask) : "memory");
}
__device__ __forceinline__ void prefetch_l2(const void* p, uint32_t bytes) { asm volatile("cp.async.bulk.prefetch.L2.global [%0], %1;" ::"l"(p), "r"(bytes) : "memory"); }
__device__ __forceinline__ void prefetch_tmap(const CUtensorMap* m) { asm volatile("prefetch.tensormap [%0];" ::"l"(m) : "memory"); }

__device__ __forceinline__ void wg_fence() { asm volatile("wgmma.fence.sync.aligned;" ::: "memory"); }
__device__ __forceinline__ void wg_commit() { asm volatile("wgmma.commit_group.sync.aligned;" ::: "memory"); }
template <int N> __device__ __forceinline__ void wg_wait() { asm volatile("wgmma.wait_group.sync.aligned %0;" ::"n"(N) : "memory"); }
__device__ __forceinline__ uint64_t mkdesc(uint32_t addr, uint32_t lbo, uint32_t sbo, uint32_t mode) {
    return (uint64_t)((addr & 0x3FFFF) >> 4) | ((uint64_t)(lbo >> 4) << 16) | ((uint64_t)(sbo >> 4) << 32) | ((uint64_t)mode << 62);
}

__device__ __forceinline__ void mma16816(float (&c)[4], uint32_t a0, uint32_t a1, uint32_t a2, uint32_t a3, uint32_t b0, uint32_t b1) {
    asm("mma.sync.aligned.m16n8k16.row.col.f32.bf16.bf16.f32 {%0,%1,%2,%3},{%4,%5,%6,%7},{%8,%9},{%0,%1,%2,%3};"
                 : "+f"(c[0]), "+f"(c[1]), "+f"(c[2]), "+f"(c[3]) : "r"(a0), "r"(a1), "r"(a2), "r"(a3), "r"(b0), "r"(b1));
}
__device__ __forceinline__ void mma1688(float (&c)[4], uint32_t a0, uint32_t a1, uint32_t b0) {
    asm("mma.sync.aligned.m16n8k8.row.col.f32.bf16.bf16.f32 {%0,%1,%2,%3},{%4,%5},{%6},{%0,%1,%2,%3};"
                 : "+f"(c[0]), "+f"(c[1]), "+f"(c[2]), "+f"(c[3]) : "r"(a0), "r"(a1), "r"(b0));
}
__device__ __forceinline__ void ldsm_x4(uint32_t& r0, uint32_t& r1, uint32_t& r2, uint32_t& r3, uint32_t a) {
    asm volatile("ldmatrix.sync.aligned.m8n8.x4.shared.b16 {%0,%1,%2,%3}, [%4];" : "=r"(r0), "=r"(r1), "=r"(r2), "=r"(r3) : "r"(a) : "memory");
}
__device__ __forceinline__ void ldsm_x4_t(uint32_t& r0, uint32_t& r1, uint32_t& r2, uint32_t& r3, uint32_t a) {
    asm volatile("ldmatrix.sync.aligned.m8n8.x4.trans.shared.b16 {%0,%1,%2,%3}, [%4];" : "=r"(r0), "=r"(r1), "=r"(r2), "=r"(r3) : "r"(a) : "memory");
}
__device__ __forceinline__ void ldsm_x2(uint32_t& r0, uint32_t& r1, uint32_t a) {
    asm volatile("ldmatrix.sync.aligned.m8n8.x2.shared.b16 {%0,%1}, [%2];" : "=r"(r0), "=r"(r1) : "r"(a) : "memory");
}
__device__ __forceinline__ void ldsm_x2_t(uint32_t& r0, uint32_t& r1, uint32_t a) {
    asm volatile("ldmatrix.sync.aligned.m8n8.x2.trans.shared.b16 {%0,%1}, [%2];" : "=r"(r0), "=r"(r1) : "r"(a) : "memory");
}
__device__ __forceinline__ void stsm_x4(uint32_t a, uint32_t r0, uint32_t r1, uint32_t r2, uint32_t r3) {
    asm volatile("stmatrix.sync.aligned.m8n8.x4.shared.b16 [%0], {%1,%2,%3,%4};" ::"r"(a), "r"(r0), "r"(r1), "r"(r2), "r"(r3) : "memory");
}
__device__ __forceinline__ void stsm_x4_t(uint32_t a, uint32_t r0, uint32_t r1, uint32_t r2, uint32_t r3) {
    asm volatile("stmatrix.sync.aligned.m8n8.x4.trans.shared.b16 [%0], {%1,%2,%3,%4};" ::"r"(a), "r"(r0), "r"(r1), "r"(r2), "r"(r3) : "memory");
}
__device__ __forceinline__ void stsm_x2(uint32_t a, uint32_t r0, uint32_t r1) {
    asm volatile("stmatrix.sync.aligned.m8n8.x2.shared.b16 [%0], {%1,%2};" ::"r"(a), "r"(r0), "r"(r1) : "memory");
}
__device__ __forceinline__ uint32_t movm_t(uint32_t a) {
    uint32_t d;
    asm volatile("movmatrix.sync.aligned.m8n8.trans.b16 %0, %1;" : "=r"(d) : "r"(a));
    return d;
}
__device__ __forceinline__ uint32_t lds32(uint32_t a) { uint32_t v; asm volatile("ld.shared.u32 %0, [%1];" : "=r"(v) : "r"(a) : "memory"); return v; }
__device__ __forceinline__ uint32_t ldsv32(uint32_t a) { uint32_t v; asm volatile("ld.volatile.shared.u32 %0, [%1];" : "=r"(v) : "r"(a) : "memory"); return v; }
__device__ __forceinline__ void sts32(uint32_t a, uint32_t v) { asm volatile("st.shared.u32 [%0], %1;" ::"r"(a), "r"(v) : "memory"); }
__device__ __forceinline__ uint4 lds128(uint32_t a) { uint4 v; asm volatile("ld.shared.v4.u32 {%0,%1,%2,%3}, [%4];" : "=r"(v.x), "=r"(v.y), "=r"(v.z), "=r"(v.w) : "r"(a) : "memory"); return v; }
__device__ __forceinline__ void sts128(uint32_t a, uint4 v) { asm volatile("st.shared.v4.u32 [%0], {%1,%2,%3,%4};" ::"r"(a), "r"(v.x), "r"(v.y), "r"(v.z), "r"(v.w) : "memory"); }

__device__ __forceinline__ void stg128(void* p, uint4 v) { asm volatile("st.global.v4.u32 [%0], {%1,%2,%3,%4};" ::"l"(p), "r"(v.x), "r"(v.y), "r"(v.z), "r"(v.w) : "memory"); }

__device__ __forceinline__ uint4 ldg128(const void* p) { uint4 v; asm volatile("ld.global.v4.u32 {%0,%1,%2,%3}, [%4];" : "=r"(v.x), "=r"(v.y), "=r"(v.z), "=r"(v.w) : "l"(p) : "memory"); return v; }
__device__ __forceinline__ uint2 ldg64(const void* p) { uint2 v; asm volatile("ld.global.v2.u32 {%0,%1}, [%2];" : "=r"(v.x), "=r"(v.y) : "l"(p) : "memory"); return v; }
__device__ __forceinline__ uint32_t ldg32(const void* p) { uint32_t v; asm volatile("ld.global.u32 %0, [%1];" : "=r"(v) : "l"(p) : "memory"); return v; }

__device__ __forceinline__ uint32_t pack2(float lo, float hi) {
    uint32_t r;
    asm("cvt.rn.bf16x2.f32 %0, %1, %2;" : "=r"(r) : "f"(hi), "f"(lo));
    return r;
}
__device__ __forceinline__ float bf_lo(uint32_t v) { return __uint_as_float(v << 16); }
__device__ __forceinline__ float bf_hi(uint32_t v) { return __uint_as_float(v & 0xFFFF0000u); }
__device__ __forceinline__ float rbf(float x) { return __uint_as_float(pack2(0.f, x) & 0xFFFF0000u); }
__device__ __forceinline__ float ex2(float x) { float r; asm("ex2.approx.ftz.f32 %0, %1;" : "=f"(r) : "f"(x)); return r; }

__device__ __forceinline__ float2 ln_finish(float sum, float sumsq) {
    const float m = sum * (1.0f / DM);
    const float v = fmaxf(fmaf(sumsq, 1.0f / DM, -m * m), 0.f);
    float s, r;
    asm("sqrt.approx.ftz.f32 %0, %1;" : "=f"(s) : "f"(rbf(rbf(v) + 1e-5f)));
    asm("rcp.approx.ftz.f32 %0, %1;" : "=f"(r) : "f"(rbf(s)));
    return make_float2(m, r);
}
__device__ __forceinline__ uint32_t ln_finish_packed(float sum, float sumsq) {
    const float m = sum * (1.0f / DM);
    const float v = fmaxf(fmaf(sumsq, 1.0f / DM, -m * m), 0.f);
    float s;
    asm("sqrt.approx.ftz.f32 %0, %1;" : "=f"(s) : "f"(rbf(rbf(v) + 1e-5f)));
    return pack2(s, m);
}
__device__ __forceinline__ float frsq(float x) { float r; asm("rsqrt.approx.ftz.f32 %0, %1;" : "=f"(r) : "f"(x)); return r; }
__device__ __forceinline__ float frcp(float x) { float r; asm("rcp.approx.ftz.f32 %0, %1;" : "=f"(r) : "f"(x)); return r; }
__device__ __forceinline__ bool elect_one() {
    uint32_t p;
    asm volatile("{\n.reg .pred p;\nelect.sync _|p, 0xffffffff;\nselp.u32 %0, 1, 0, p;\n}" : "=r"(p));
    return p != 0;
}
__device__ __forceinline__ void cluster_arrive_relaxed() { asm volatile("barrier.cluster.arrive.relaxed.aligned;" ::: "memory"); }
__device__ __forceinline__ void cluster_wait() { asm volatile("barrier.cluster.wait.aligned;" ::: "memory"); }
__device__ __forceinline__ unsigned long long ld_ll(const unsigned long long* p) {
    unsigned long long v;
    asm volatile("ld.relaxed.gpu.global.b64 %0, [%1];" : "=l"(v) : "l"(p) : "memory");
    return v;
}
__device__ __forceinline__ void st_ll(unsigned long long* p, uint32_t payload, uint32_t tag) {
    const unsigned long long v = (unsigned long long)payload | ((unsigned long long)tag << 32);
    asm volatile("st.relaxed.gpu.global.b64 [%0], %1;" ::"l"(p), "l"(v) : "memory");
}
__device__ __forceinline__ uint4 ld_ll4(const uint4* p) {
    uint4 v;
    asm volatile("{\n.reg .b128 t;\n.reg .b64 a, b;\nld.relaxed.gpu.global.b128 t, [%4];\nmov.b128 {a, b}, t;\nmov.b64 {%0, %1}, a;\nmov.b64 {%2, %3}, b;\n}"
                 : "=r"(v.x), "=r"(v.y), "=r"(v.z), "=r"(v.w) : "l"(p) : "memory");
    return v;
}
__device__ __forceinline__ void st_ll4(uint4* p, uint32_t x, uint32_t y, uint32_t z, uint32_t w) {
    asm volatile("{\n.reg .b128 t;\n.reg .b64 a, b;\nmov.b64 a, {%1, %2};\nmov.b64 b, {%3, %4};\nmov.b128 t, {a, b};\nst.relaxed.gpu.global.b128 [%0], t;\n}"
                 ::"l"(p), "r"(x), "r"(y), "r"(z), "r"(w) : "memory");
}

__device__ __forceinline__ void bulk_s2g(void* dst, uint32_t src, uint32_t bytes) {
    asm volatile("cp.async.bulk.global.shared::cta.bulk_group [%0], [%1], %2;" ::"l"(dst), "r"(src), "r"(bytes) : "memory");
}
__device__ __forceinline__ void bulk_commit() { asm volatile("cp.async.bulk.commit_group;" ::: "memory"); }
__device__ __forceinline__ void bulk_wait() { asm volatile("cp.async.bulk.wait_group 0;" ::: "memory"); }
__device__ __forceinline__ void fence_async_global() { asm volatile("fence.proxy.async.global;" ::: "memory"); }
__device__ __forceinline__ void fence_release() { asm volatile("fence.release.gpu;" ::: "memory"); }
__device__ __forceinline__ void fence_acquire() { asm volatile("fence.acquire.gpu;" ::: "memory"); }
__device__ __forceinline__ void ll_check5(uint4 (&f)[5], const uint4* p, uint32_t mark) {
#define LL_LD(i, a, b, c, d) "ld.relaxed.gpu.global.b128 q, [%20 + " #i "];\nmov.b128 {u, v}, q;\nmov.b64 {%" #a ", %" #b "}, u;\nmov.b64 {%" #c ", %" #d "}, v;\n"
    asm volatile("{\n.reg .pred p;\n.reg .b32 t, n, m;\n.reg .b128 q;\n.reg .b64 u, v;\nmov.u32 n, 0x7FFFF;\n"
                 "L:\nlop3.b32 t, %0, %4, %21, 0x7E;\nlop3.b32 t, t, %8, %21, 0xF6;\nlop3.b32 t, t, %12, %21, 0xF6;\nlop3.b32 t, t, %16, %21, 0xF6;\n"
                 "shr.u32 m, n, 18;\nand.b32 t, t, m;\nsetp.ne.u32 p, t, 0;\nvote.sync.any.pred p, p, 0xffffffff;\n@!p bra.uni D;\n"
                 LL_LD(0, 0, 1, 2, 3) LL_LD(512, 4, 5, 6, 7) LL_LD(1024, 8, 9, 10, 11) LL_LD(1536, 12, 13, 14, 15) LL_LD(2048, 16, 17, 18, 19)
                 "sub.u32 n, n, 1;\nbra.uni L;\nD:\n}"
                 : "+r"(f[0].x), "+r"(f[0].y), "+r"(f[0].z), "+r"(f[0].w), "+r"(f[1].x), "+r"(f[1].y), "+r"(f[1].z), "+r"(f[1].w), "+r"(f[2].x), "+r"(f[2].y),
                   "+r"(f[2].z), "+r"(f[2].w), "+r"(f[3].x), "+r"(f[3].y), "+r"(f[3].z), "+r"(f[3].w), "+r"(f[4].x), "+r"(f[4].y), "+r"(f[4].z), "+r"(f[4].w)
                 : "l"(p), "r"(mark) : "memory");
}
template<int TA, int TB>
__device__ __forceinline__ void wgmma_n192(float (&d)[96], uint64_t da, uint64_t db, int scale_d) {
  asm volatile("{\n.reg .pred p;\nsetp.ne.b32 p, %98, 0;\n"
    "wgmma.mma_async.sync.aligned.m64n192k16.f32.bf16.bf16 "
    "{%0, %1, %2, %3, %4, %5, %6, %7, %8, %9, %10, %11, %12, %13, %14, %15, %16, %17, %18, %19, %20, %21, %22, %23, %24, %25, %26, %27, %28, %29, %30, %31, %32, %33, %34, %35, %36, %37, %38, %39, %40, %41, %42, %43, %44, %45, %46, %47, %48, %49, %50, %51, %52, %53, %54, %55, %56, %57, %58, %59, %60, %61, %62, %63, %64, %65, %66, %67, %68, %69, %70, %71, %72, %73, %74, %75, %76, %77, %78, %79, %80, %81, %82, %83, %84, %85, %86, %87, %88, %89, %90, %91, %92, %93, %94, %95}, %96, %97, p, 1, 1, %99, %100;\n}\n"
    : "+f"(d[0]), "+f"(d[1]), "+f"(d[2]), "+f"(d[3]), "+f"(d[4]), "+f"(d[5]), "+f"(d[6]), "+f"(d[7]), "+f"(d[8]), "+f"(d[9]), "+f"(d[10]), "+f"(d[11]), "+f"(d[12]), "+f"(d[13]), "+f"(d[14]), "+f"(d[15]), "+f"(d[16]), "+f"(d[17]), "+f"(d[18]), "+f"(d[19]), "+f"(d[20]), "+f"(d[21]), "+f"(d[22]), "+f"(d[23]), "+f"(d[24]), "+f"(d[25]), "+f"(d[26]), "+f"(d[27]), "+f"(d[28]), "+f"(d[29]), "+f"(d[30]), "+f"(d[31]), "+f"(d[32]), "+f"(d[33]), "+f"(d[34]), "+f"(d[35]), "+f"(d[36]), "+f"(d[37]), "+f"(d[38]), "+f"(d[39]), "+f"(d[40]), "+f"(d[41]), "+f"(d[42]), "+f"(d[43]), "+f"(d[44]), "+f"(d[45]), "+f"(d[46]), "+f"(d[47]), "+f"(d[48]), "+f"(d[49]), "+f"(d[50]), "+f"(d[51]), "+f"(d[52]), "+f"(d[53]), "+f"(d[54]), "+f"(d[55]), "+f"(d[56]), "+f"(d[57]), "+f"(d[58]), "+f"(d[59]), "+f"(d[60]), "+f"(d[61]), "+f"(d[62]), "+f"(d[63]), "+f"(d[64]), "+f"(d[65]), "+f"(d[66]), "+f"(d[67]), "+f"(d[68]), "+f"(d[69]), "+f"(d[70]), "+f"(d[71]), "+f"(d[72]), "+f"(d[73]), "+f"(d[74]), "+f"(d[75]), "+f"(d[76]), "+f"(d[77]), "+f"(d[78]), "+f"(d[79]), "+f"(d[80]), "+f"(d[81]), "+f"(d[82]), "+f"(d[83]), "+f"(d[84]), "+f"(d[85]), "+f"(d[86]), "+f"(d[87]), "+f"(d[88]), "+f"(d[89]), "+f"(d[90]), "+f"(d[91]), "+f"(d[92]), "+f"(d[93]), "+f"(d[94]), "+f"(d[95])
    : "l"(da), "l"(db), "r"(scale_d), "n"(TA), "n"(TB));
}

template<int TA, int TB>
__device__ __forceinline__ void wgmma_n48(float (&d)[24], uint64_t da, uint64_t db, int scale_d) {
  asm volatile("{\n.reg .pred p;\nsetp.ne.b32 p, %26, 0;\n"
    "wgmma.mma_async.sync.aligned.m64n48k16.f32.bf16.bf16 "
    "{%0, %1, %2, %3, %4, %5, %6, %7, %8, %9, %10, %11, %12, %13, %14, %15, %16, %17, %18, %19, %20, %21, %22, %23}, %24, %25, p, 1, 1, %27, %28;\n}\n"
    : "+f"(d[0]), "+f"(d[1]), "+f"(d[2]), "+f"(d[3]), "+f"(d[4]), "+f"(d[5]), "+f"(d[6]), "+f"(d[7]), "+f"(d[8]), "+f"(d[9]), "+f"(d[10]), "+f"(d[11]), "+f"(d[12]), "+f"(d[13]), "+f"(d[14]), "+f"(d[15]), "+f"(d[16]), "+f"(d[17]), "+f"(d[18]), "+f"(d[19]), "+f"(d[20]), "+f"(d[21]), "+f"(d[22]), "+f"(d[23])
    : "l"(da), "l"(db), "r"(scale_d), "n"(TA), "n"(TB));
}

__device__ __forceinline__ void wgmma_rs80(float (&d)[40], const uint4& a, uint64_t db, int scale_d) {
  asm volatile("{\n.reg .pred p;\nsetp.ne.b32 p, %45, 0;\n"
    "wgmma.mma_async.sync.aligned.m64n80k16.f32.bf16.bf16 {%0,%1,%2,%3,%4,%5,%6,%7,%8,%9,%10,%11,%12,%13,%14,%15,%16,%17,%18,%19,%20,%21,%22,%23,%24,%25,%26,%27,%28,%29,%30,%31,%32,%33,%34,%35,%36,%37,%38,%39}, {%40,%41,%42,%43}, %44, p, 1, 1, 1;\n}\n"
    : "+f"(d[0]), "+f"(d[1]), "+f"(d[2]), "+f"(d[3]), "+f"(d[4]), "+f"(d[5]), "+f"(d[6]), "+f"(d[7]), "+f"(d[8]), "+f"(d[9]), "+f"(d[10]), "+f"(d[11]), "+f"(d[12]), "+f"(d[13]), "+f"(d[14]), "+f"(d[15]), "+f"(d[16]), "+f"(d[17]), "+f"(d[18]), "+f"(d[19]), "+f"(d[20]), "+f"(d[21]), "+f"(d[22]), "+f"(d[23]), "+f"(d[24]), "+f"(d[25]), "+f"(d[26]), "+f"(d[27]), "+f"(d[28]), "+f"(d[29]), "+f"(d[30]), "+f"(d[31]), "+f"(d[32]), "+f"(d[33]), "+f"(d[34]), "+f"(d[35]), "+f"(d[36]), "+f"(d[37]), "+f"(d[38]), "+f"(d[39])
    : "r"(a.x), "r"(a.y), "r"(a.z), "r"(a.w), "l"(db), "r"(scale_d));
}

__device__ __forceinline__ void wgmma_ss80(float (&d)[40], uint64_t da, uint64_t db) {
  asm volatile("wgmma.mma_async.sync.aligned.m64n80k16.f32.bf16.bf16 {%0,%1,%2,%3,%4,%5,%6,%7,%8,%9,%10,%11,%12,%13,%14,%15,%16,%17,%18,%19,%20,%21,%22,%23,%24,%25,%26,%27,%28,%29,%30,%31,%32,%33,%34,%35,%36,%37,%38,%39}, %40, %41, 1, 1, 1, 0, 1;"
    : "+f"(d[0]), "+f"(d[1]), "+f"(d[2]), "+f"(d[3]), "+f"(d[4]), "+f"(d[5]), "+f"(d[6]), "+f"(d[7]), "+f"(d[8]), "+f"(d[9]), "+f"(d[10]), "+f"(d[11]), "+f"(d[12]), "+f"(d[13]), "+f"(d[14]), "+f"(d[15]), "+f"(d[16]), "+f"(d[17]), "+f"(d[18]), "+f"(d[19]), "+f"(d[20]), "+f"(d[21]), "+f"(d[22]), "+f"(d[23]), "+f"(d[24]), "+f"(d[25]), "+f"(d[26]), "+f"(d[27]), "+f"(d[28]), "+f"(d[29]), "+f"(d[30]), "+f"(d[31]), "+f"(d[32]), "+f"(d[33]), "+f"(d[34]), "+f"(d[35]), "+f"(d[36]), "+f"(d[37]), "+f"(d[38]), "+f"(d[39])
    : "l"(da), "l"(db));
}

__device__ const __align__(1024) uint32_t c_fft[11264] = {
0x2ddc2dba,0x2fe62eb5,0x2ed02eb5,0xafffaf6e,0x2e1f2dfe,0x2e3f2fbc,0x2f022ee9,0xad27af30,0x2e5e2e3f,0x1fd92b5e,0x2f302f1a,0x244ea875,0x2e992e7c,0xad96a993,0x2f5a2f46,0x2e992c32,
0xad00ad72,0xa17eac32,0xa17ea515,0xabb79cb6,0xac07ac87,0x2dfe29f1,0x1fd99648,0xafedae99,0xa9f1ab05,0x2fd42fbc,0x26a1244e,0xad96af91,0xa765a8d5,0x2aaa2e3f,0x29932875,0x2515a8d5,
0xae99adfe,0xb000aee9,0xaf6eafbc,0x2c872f30,0xaf80af1a,0xac32af02,0xae7caf02,0xaaaa217e,0xaff4afc9,0x2b5e9cb6,0xad27addc,0xaff4ae7c,0xafedb000,0x2ffc2eb5,0xab05ac5d,0xacd8af5a,
0x2c072d27,0x9fd92bb7,0xadfead00,0x2fed2e1f,0x25db2993,0xaf6eacb0,0xaf6eaed0,0x2c5d2f46,0xa5151648,0xaddcafdd,0xafffafd4,0xac321648,0xabb7a934,0x28d5a814,0xafa0afed,0xaff4af30,
0x2f302e3f,0x2fed2f1a,0x28142b5e,0x2934a875,0x30002fc9,0x26a12ddc,0xa5db1cb6,0x30002e7c,0x2f462fd4,0xaed0aa4e,0xacb0aa4e,0x29932e99,0x2d272e5e,0xae3faffc,0xaf02adfe,0xae1fa814,
0xa9f1acd8,0x26a1ab05,0x2fd42ffc,0xad96afed,0x2515a30e,0x2fff2e1f,0x2ddc2f1a,0x2c32a30e,0x2d272aaa,0x28752e7c,0x28752c32,0x2fa02f80,0x2f912e99,0xaee9a9f1,0xa8141648,0x9fd92c87,
0xafa0ae7c,0xafafaf46,0x2d002993,0xafa0ac32,0xaf91b000,0x244eac5d,0x2fbc2eb5,0xab05af5a,0xac87ae5e,0x30002dfe,0x2f6e2ffc,0x2e992814,0x1cb6a875,0x25152e1f,0x2c322e1f,0x2d722ff4,
0x27652c87,0xa9932a4e,0xaaaaadba,0xa5152c87,0xabb7a44e,0xafa0af30,0x28d59fd9,0xaff4ae5e,0xaf91ae1f,0x2814abb7,0x2ee92d00,0x1fd9ad27,0xaf5aafff,0x2fd42ed0,0x2fd42fe6,0x30002ddc,
0x2f462f6e,0x2c322fdd,0x2e7c2fdd,0xa993b000,0xab5e2934,0xafafacd8,0xad00244e,0x2f1a2dfe,0xaee9afaf,0x2f30a17e,0xadfeaff8,0xafbca30e,0x2c5da765,0xa9f12ddc,0x2d969cb6,0x2c5dacb0,
0x2bb7a993,0x2f1aa515,0x2f1a2765,0xaff4aaaa,0x2e5e2fd4,0xab052dba,0x29342f6e,0x2ee9a6a1,0xadba1fd9,0xa5dbafed,0xafddac07,0xaa4e2dfe,0xacb0aff8,0x2ddc2f02,0x9cb6ae3f,0xa765aff8,
0xaeb5af91,0xaa4eafed,0x9648ae5e,0xac5d2d4d,0x2ddca17e,0x2e7c2e3f,0x2fc92e3f,0x1cb6afa0,0x2bb72fe6,0xaff8a993,0xab5e2aaa,0x2bb72fc9,0xafbcaa4e,0x2f30a5db,0xadfeafdd,0xaee9adba,
0xacd828d5,0xaf91230e,0xaf30af02,0x2c072fa0,0xac5dafff,0x2dbaac32,0x2dbaa515,0xae99addc,0x2fc929f1,0xa9932eb5,0x2aaa2fdd,0x2fe629f1,0xa30e2dfe,0xa17eafed,0xaff8ac07,0xafaf1fd9,
0x2dfe2faf,0x28142ff8,0xae5e217e,0x2ffc230e,0xaf5aa515,0xac87af46,0xa6a1af80,0xaf5a2765,0x1cb6ae99,0x2e7c2dba,0x2fc92dba,0x2ddcac5d,0x2f1a2ee9,0xafafab05,0xad002934,0xab5e2e5e,
0x2dbaa814,0x2fdd9fd9,0x25db2f91,0x2a4eaee9,0x27652faf,0xaf4628d5,0xaf80ae1f,0xa5152faf,0xafa0addc,0x2e3fac32,0x2e3fa515,0xa17eafff,0x2dfea6a1,0xacd82dba,0x244e2f6e,0x29342fd4,
0xad27afc9,0xa30eafff,0x2faf2d72,0xad27ae7c,0x2ffc2a4e,0x28142fdd,0xae5e25db,0x2dfe2dba,0xac5d2c07,0xaa4eaf91,0x9648af30,0xaeb5acd8,0xa993aff4,0x2c322f1a,0x2e7c2f1a,0x2f462bb7,
0xae7c26a1,0xafff1648,0x2d72aa4e,0xafc926a1,0x230eaee9,0x2ff89fd9,0x217e2f91,0x2fafa814,0x2d4d2fa0,0xafed230e,0xae5eaf02,0xaf9128d5,0xb000aaaa,0x2fdda515,0x2fdd2765,0x2f6ea993,
0x9cb63000,0xacb02fd4,0xa7652fd4,0x2ddcaf5a,0x217eaffc,0x2ff4ac07,0x2875afbc,0xaff82934,0xa44e2ff4,0xadfea8d5,0xa9342fa0,0x2cd82bb7,0x25dbafe6,0x16482f46,0x29f1af80,0x25dbafc9,
0x2ff41cb6,0x2e1f2765,0x2e1f2cb0,0xa875addc,0xafbca5db,0x1fd9af5a,0xad4dad96,0xacd82fdd,0x2f5a2934,0xaeb52ee9,0x2c5d2e5e,0x3000ab05,0xaed0ab5e,0x2f80a30e,0xaaaaaf02,0xacb0ab5e,
0x25dbaffc,0x2d96afbc,0x2f5aac07,0xafdd2934,0xaaaa2fa0,0xafc92875,0xafe62875,0x29932d27,0x2d00aed0,0x28d52d72,0x2ff89cb6,0x2d00afe6,0xae5e2d96,0x2d4dafd4,0xaf91a6a1,0xafed29f1,
0xafbca17e,0xad4da875,0x1fd9aff4,0xacd82ff8,0x2e992aaa,0xaa4e2fe6,0xaa4e2fc9,0x2fd4a993,0xacb0ad96,0x2fffac87,0x2d72aeb5,0xa765ad96,0x28752f30,0xab5eac07,0xaf1a2cd8,0xae3f2f91,
0xa9342ff4,0xae5e2fa0,0xaee9a8d5,0x2b052bb7,0x2d96aed0,0x2eb59cb6,0x2c872d72,0x2d96afe6,0xaf802c5d,0x2765af6e,0xa515af6e,0xaf4625db,0x2ff8a44e,0xaff42d4d,0xa8752ffc,0xa17e2ee9,
0x2f5a244e,0x2c5d2934,0xaeb52dfe,0x3000acd8,0xacb0ad00,0x2d72aff8,0x2fffa8d5,0xa765ad00,0x217e2f80,0xaf022515,0xaf02a765,0xaf1a2f46,0x2b05afdd,0xa8142f5a,0x2c072d96,0x2d4d25db,
0x2b5eafe6,0x2f02af80,0x230e2f46,0x2b5eafc9,0xaf302d96,0xacd8a6a1,0x2c07afd4,0xaf9129f1,0x2fdda44e,0xad962ffc,0xaf5a2d4d,0xa5db2ee9,0xad72abb7,0x2e7ca17e,0x2fc9a17e,0x2fffad00,
0xaed0a5db,0xaaaaa9f1,0x2f809648,0xacb0a5db,0x28752e5e,0xaf1a2f91,0xab5ead4d,0xae3f2fed,0x2b05aff8,0x2c072875,0xa8142ff4,0x2d4d217e,0xaf6e2d72,0x2eb5afc9,0x2eb5ae7c,0x2dbaafff,
0xaf802f5a,0xafc92e99,0xafe62e99,0x2f46ad96,0x28d52b05,0xaf022fed,0x230e2cd8,0x2fa0affc,0x2fbcaf02,0xa9342d27,0x2ffcae1f,0x2c07ae3f,0xa6a1ac32,0x2a4e9cb6,0x9648ad72,0xa6a1a515,
0x28752aaa,0xa8d52cb0,0xa8d52ed0,0x2e3faf80,0x2fedaeb5,0x29349648,0x2f30aa4e,0x2814ac5d,0x1648ad4d,0x2e99acd8,0x2c87afbc,0xa9f11fd9,0xafe62d27,0x2fffafaf,0xaddc230e,0xaed02d27,
0x2fd4af30,0x2f6eae5e,0x2dbaa44e,0xa6a19fd9,0x1cb6ad27,0x2fe6aff4,0x2ed0aff4,0xad722b5e,0xafaf2cb0,0x2e1faf46,0xa8d5a993,0xafaf2ed0,0xac072f6e,0x2934ac87,0xaffc2e99,0xafbc3000,
0xa44eab5e,0x2b05ad00,0x2f91afaf,0xafbc2f1a,0xafd42d72,0x1648a765,0x1648acb0,0xafdd2fff,0xac322f5a,0xaaaa26a1,0xaf802c87,0xae7c2f5a,0x2d009fd9,0xae1f2cd8,0xad272fbc,0xabb72d4d,
0xaffc2f02,0xaee92e1f,0x244ead27,0xad4d2e3f,0xa9f12e7c,0xafdd2f80,0xaeb52aaa,0xa9f12c32,0x2d72a5db,0xafe63000,0xaed03000,0x9cb626a1,0x2fa0afbc,0xaf022f91,0x230e2b05,0x28d5a44e,
0x96482c07,0xac872d4d,0xae992b05,0x29f1a814,0x2ed0abb7,0xa9932b5e,0xaf462ff8,0x2cb0abb7,0x2f1aafff,0xa30e2765,0xa30e2cb0,0x2e1fad72,0x1fd9ac5d,0x244e9648,0x2e5eaa4e,0x2f30aeb5,
0x2ff8aed0,0x2e3faddc,0xaf022fff,0x2ff8afe6,0x2d4daf6e,0x2ee9ae99,0xa44e2c87,0x2ffcb000,0xa6a1a814,0x2f6eaf30,0x2dbaa934,0x2fd4afed,0xaf462d00,0x2fc9afa0,0x2fe6afa0,0x2f80afaf,
0x2515ac5d,0x2d72ad96,0x1cb629f1,0x2c32ac5d,0xad002814,0x2d27ad4d,0x2e1fab05,0x2bb7ac07,0xaffc2f1a,0x2cd8ad00,0x2fedafaf,0x2b05ab5e,0xadba2f80,0x2c87acb0,0x2c87aed0,0x2a4eaaaa,
0x2f802f6e,0x2fc92fdd,0x2fe62fdd,0xaf46b000,0x2fa02f91,0x2bb72e5e,0x2ff42fed,0xa8d5ad4d,0x2fbc2faf,0xa934217e,0x2ffc2ff8,0x2c07230e,0x2fd42fc9,0xaf5aad72,0x30002fff,0x2fd42e7c,
0x2bb72aaa,0x2f1a2cb0,0x2f1a2ed0,0xaff4af80,0x2cd82c5d,0x2f303000,0x2f912f5a,0xac07aeb5,0x2dba2d4d,0x25db2cd8,0x2fdd2fbc,0x2a4e9fd9,0x2e7c2e1f,0xad72a875,0x2fff2ff4,0x2fc92e1f,
0xa6a1a934,0x29f1a44e,0x2d962cd8,0xafd4adfe,0x1cb6a17e,0x2fe62e3f,0x2ed02e3f,0xad72afa0,0x28752515,0x2d272f80,0x2fa02f46,0x2875a765,0x2c072a4e,0xa93425db,0x2ffc2fdd,0x2fbc2dba,
0xae5eaf1a,0xa934ae3f,0x2b052875,0xaee9ab5e,0xac5dad72,0x2dba2765,0x2dba2cb0,0xae99afff,0xa765aa4e,0x2f802fd4,0x2f462e99,0x2515aa4e,0x230e9fd9,0x217e2cd8,0x2ff82fbc,0x2faf2d4d,
0xaffcafaf,0xaee9aff8,0x244ea17e,0xad4da30e,0xaf6eafe6,0x25dbaaaa,0x2c5d2993,0xaf6eafc9,0xad72ae99,0x2fe62dba,0x2ed02dba,0x1cb6ac5d,0xa8d5ac07,0x2bb72f30,0x2ff42f91,0x2fa02cd8,
0xadbaac07,0xafddad4d,0xa5dbab05,0xaa4e2814,0xafc9af02,0xaaaaaf1a,0x2993217e,0xafe6af02,0xafa0afff,0x2e3f2765,0x2e3f2cb0,0xa17ead72,0xad4daeb5,0x2e5e3000,0x2fed2f5a,0x2f912c5d,
0xa17e2765,0xad001cb6,0xabb7addc,0xa17e2cb0,0xad4daa4e,0xaee9afdd,0x244ea5db,0xaffcadba,0xafd4aee9,0x29f1a934,0x2d962b05,0xa6a1ae5e,0xaf46aff4,0x2fc92f1a,0x2fe62f1a,0x2f802bb7,
0x2cb02eb5,0x1cb62dba,0xaddcaf6e,0x27652eb5,0xa30e2814,0xaff8ad4d,0xa17eab05,0xafafac07,0xadfeab5e,0xa44eae3f,0x2cd82875,0xa934af1a,0xb000af80,0x2fdd2cb0,0x2fdd2ed0,0x2f6e2aaa,
0x2d723000,0x25152fd4,0x2c322fd4,0x1cb6af5a,0xae1f9fd9,0xae3faee9,0xaf02a814,0x2d272f91,0xacd8aff4,0x2ffc28d5,0xab05afa0,0xafedabb7,0x2e992515,0xad962aaa,0x2f5a2993,0x2e99a765,
0x2ff42ddc,0x2e1f2ed0,0x2e1f2fe6,0xa875afff,0xa8142c87,0xaffca9f1,0xadfe1648,0x2e5e2e99,0xaf5aaf30,0x2eb5a814,0xac5dafed,0xb000a934,0x2c32a8d5,0xa9932e3f,0x2f462875,0x2e7ca8d5,
0x2e991fd9,0x30002814,0x2f6e2ee9,0xac87af91,0x29932fa0,0xaed02875,0xacb02875,0x2f462d27,0xaff4ac32,0x2b5eaddc,0xad27afff,0xaff4a515,0x244ead96,0x1fd92fd4,0x2f3026a1,0x2e5ea9f1,
0x2814ad27,0x2dfeabb7,0x2ffc2d00,0xae5eae1f,0x2e992f80,0xaa4e2e7c,0xaa4e2c32,0x2fd42aaa,0xae7c1648,0x9cb6afdd,0xaddcafd4,0xafc91648,0xa875af91,0x2b5e2fbc,0x2f1a244e,0x2e3fab05,
0xab05aff4,0x244eafa0,0x2fbc28d5,0xaf91abb7,0x30002c32,0x26a12fff,0xa5db2ddc,0x30002515,0xaaaa2c5d,0xac32af6e,0xae7caf6e,0xaf8025db,0xad27afed,0x2e3f2dfe,0x2f021fd9,0x2e1fac07,
0xaf5aae5e,0xac5daf30,0x2eb59fd9,0xb000a44e,0x2e7ca30e,0x2ddc2e1f,0x1cb62f1a,0x2fc9a30e,0x217e2f46,0xaf02acb0,0xaf02aed0,0xaf1a2993,0xaf30ae99,0x2fbc29f1,0x2ee99648,0x2dfeac87,
0xafa0a515,0xafafa993,0x2d00aaaa,0xafa02765,0x2934ad96,0x2fed26a1,0x28142fd4,0x2f30a9f1,0x2c872fed,0xb0009fd9,0xaf6eadfe,0xae992c07,0xafffabb7,0x2fe6a17e,0x2ed0a17e,0x2ddcad00,
0xac322c87,0xaf462a4e,0x2993adba,0xae7c2c87,0xa875afed,0x2f1aab05,0x2b5e2ffc,0x2e3facd8,0x2f302e1f,0xaee92bb7,0xafbcad00,0xadfe2d27,0xaf6e9cb6,0x2eb5ac32,0x2eb5a515,0x2dbaad72,
0xaaaa2f5a,0xaed02e99,0xacb02e99,0x2f80ad96,0x2b5eaf30,0x2fafa44e,0x2d00ae5e,0xaf1a9fd9,0xac072f02,0xab05ad27,0xad4d2e1f,0x28142e3f,0x2c5daed0,0xa9f12fff,0x2d96addc,0x2c5dafe6,
0x28752f80,0xa8d52fe6,0xa8d52fc9,0x2e3faf46,0xa44eafd4,0x2f91adba,0x2b05af6e,0xafbc26a1,0x96482ffc,0xae99a44e,0xac872ee9,0x29f12d4d,0x2515aff8,0x1cb62f02,0x2d72ae3f,0x2c32aff8,
0x2eb52b05,0x2a4e2cd8,0x16482fed,0x2c5daffc,0xad72ad27,0x2cb0aff4,0x2765aff4,0xafff2b5e,0x2bb72e7c,0xaff82aaa,0xab5e2f80,0x2bb72c32,0xa814af6e,0x2b052c87,0x2d4dae99,0x2c07b000,
0x2feda8d5,0x2f30a30e,0x29342f02,0x2814afa0,0xafd49cb6,0x1648aed0,0x1648afe6,0xafdd2d72,0x2ed029f1,0xaf462eb5,0xa9932fdd,0x2cb029f1,0xad00ad4d,0x2e1f244e,0x2d27aee9,0x2bb7affc,
0x2d4daf02,0x2fbcae1f,0x2cd82d27,0x9fd9ae3f,0xaf5a2cb0,0xac87a993,0xa6a1af46,0xaf5a2ed0,0x2fffa5db,0xacb03000,0xa7653000,0x2d7226a1,0xaf1aa814,0x2fafa934,0x2d00af30,0x2b5eafed,
0x1648afbc,0x2c87affc,0x2e992934,0xa9f1ac07,0xac322faf,0xaf8028d5,0xaaaaae1f,0xae7c2faf,0x2f1aad72,0xa30e2ed0,0xa30e2fe6,0x2e1f1cb6,0xaffc26a1,0x2fedadba,0x2cd8af6e,0x2b05afd4,
0xad27ac32,0xa30ead72,0x2faf9cb6,0xad27a515,0x1fd92f6e,0xafbc2e99,0xacd8ac87,0xad4d3000,0x2c5dafbc,0x2a4e2b05,0x16482f91,0x2eb5a44e,0xaf802d00,0x2ed0afa0,0x2cb0afa0,0x2aaaafaf,
0xafe626a1,0xaddc1648,0x2fffaa4e,0xaed026a1,0x2d002c07,0xad272ffc,0xae1fa934,0xabb72fbc,0x1fd9afa0,0x2e5ea30e,0x244e2f02,0x2f30a8d5,0xadba2f46,0x2c87afe6,0x2c87afc9,0x2a4eaf80,
0xafff2d96,0xae7c2c5d,0xafc92c5d,0x2d72a9f1,0xa17e2dfe,0xaff42fbc,0xa8752ee9,0x2ff8af30,0x2fedad00,0xad4d2f1a,0x2f91ab5e,0x2e5eafaf,0x25dbae7c,0x16482993,0x29f1af46,0x25dbac32,
0xae3f2fff,0xaff82fc9,0xaff82e7c,0x2f02ad72,0x2c0725db,0xadfe2f5a,0x9fd92d96,0x2fedafdd,0x2f6eaf91,0xa6a12c07,0x2fd4acd8,0x2dbaaf30,0xa765ab5e,0x2aaaa30e,0x2993af02,0x2515ab5e,
0xa5db2dfe,0xad962ee9,0xaf5a2fbc,0x2fddaf30,0x2f46ab5e,0xa7652bb7,0x25152bb7,0x2f80aff8,0x2d00afc9,0x28d59cb6,0x2ff8addc,0x2d00ae7c,0xacd89648,0x2dfeac5d,0x2934aeb5,0x244eaa4e,
0x2c07217e,0x9fd92875,0xadfe2ff4,0x2fedaff8,0x2fddaf46,0x29f1a515,0x29f12765,0x2eb5af80,0x2515ad96,0x2ddcac87,0x2fffaeb5,0x2c32ad96,0xaf022b05,0x2fa0aee9,0x28d5ae5e,0x230ea934,
0x2f91ad00,0x2cd8ab5e,0xac072f1a,0x2f30afaf,0x2d96afc9,0x2eb5addc,0x2c879cb6,0x2d96ae7c,0xa993a6a1,0x2fc9af5a,0x2fe6af5a,0x2aaaac87,0xaff82e5e,0x2ff4affc,0x2875adfe,0x217ea814,
0x2f6eafed,0x2fd4af91,0xa6a12d4d,0x2dbaae5e,0x2515ad00,0x2fffaff8,0x2ddca8d5,0x2c32ad00,0xae1f2993,0x2fafafe6,0x2fafafc9,0x28d5aaaa,0xaf912fdd,0x2ee9af5a,0x2814ad96,0x1fd9a5db,
0x2b5eae7c,0x2f02af46,0x230e2993,0x2b5eac32,0xab059648,0x2e5eaeb5,0x2ee9ac5d,0x2934aa4e,0xafdd2e5e,0x2d96adfe,0x2f5aaffc,0x25dba814,0xaddc2faf,0x2cb0ad27,0x2765ad27,0x1cb6a30e,
0xa765a5db,0x2993a9f1,0x2aaa9648,0x2515a5db,0xaf022cd8,0x28d5a934,0x2fa0adfe,0x230ea44e,0xaf912ff8,0x2814a875,0x2ee9aff4,0x1fd9a17e,0xaa4e2ddc,0x26a1a765,0x26a1acb0,0x16489cb6,
0x2d722d96,0x25152c5d,0x2c322c5d,0x1cb6a9f1,0x2d272d4d,0xad00a814,0x2bb72c07,0x2e1f2b05,0x2cd82d00,0xaffcaf1a,0x2b052b5e,0x2fed2faf,0x2c872cb0,0xadbaaf80,0x2a4e2aaa,0x2c872ed0,
0x2e3f2ddc,0x2ff82ed0,0x2ff82fe6,0xaf02afff,0x2ee92e99,0x2d4d2f6e,0x2ffc3000,0xa44eac87,0x2f6e2f30,0xa6a12814,0x2fd42fed,0x2dba2934,0x2fc92fa0,0xaf46ad00,0x2f802faf,0x2fe62fa0,
0xac87ad4d,0x9648ac07,0x29f12814,0xae99ab05,0xa993ab5e,0x2ed02bb7,0x2cb02bb7,0xaf46aff8,0xa30ea765,0x2f1a2fff,0x2e1f2d72,0xa30eacb0,0x244e1648,0x1fd92c5d,0x2f302eb5,0x2e5e2a4e,
0xaee9ae1f,0xaffcaf02,0xad4dae3f,0x244e2d27,0xafddaf80,0xa9f1ae7c,0xa9f1ac32,0xaeb5aaaa,0xafe6b000,0x2d7225db,0x9cb6a6a1,0xaed0b000,0xaf02af91,0x2fa02fbc,0x28d5244e,0x230eab05,
0x2b052d00,0xa44e2b5e,0xafbcaf1a,0x2f912faf,0x16482765,0xafd4ad72,0xafddafff,0x16482cb0,0xaaaaa6a1,0xac32af5a,0xae7caf5a,0xaf80ac87,0xae1facd8,0x2d001fd9,0xabb7ad4d,0xad27afbc,
0x2f6e2e5e,0x2fd42f30,0xa6a11fd9,0x2dba244e,0x2fe62ff4,0x1cb62d27,0xad72ab5e,0x2ed02ff4,0x2e1f2f46,0xafafacb0,0xafafaed0,0xa8d52993,0x29342c87,0xac07af6e,0xafbcb000,0xaffcae99,
0xa8d5acb0,0x2875aaaa,0x2e3f2f80,0xa8d5aed0,0x29341648,0x2fed2eb5,0x28142c5d,0x2f302a4e,0x2e992cd8,0x16482d4d,0xa9f19fd9,0x2c872fbc,0x2fff2faf,0xafe6ad27,0xaed0ad27,0xaddca30e,
0xafc9ae99,0xaf80af5a,0x2f462d96,0xafe6ae99,0xaf02afed,0x28d5ab05,0x2fa02ffc,0x230eacd8,0xa934ad27,0x2fbc2f02,0x2c072e3f,0x2ffc2e1f,0x2a4e1cb6,0xa6a12c32,0xa6a12515,0x96482d72,
0xaaaa29f1,0xaed025db,0xacb025db,0x2f801648,0xaf1aaf91,0x2875ae5e,0xae3fafed,0xab5e2d4d,0x2c07a875,0x2b052ff8,0x2d4da17e,0xa814aff4,0x2eb52fc9,0xaf6ead72,0x2dba2fff,0x2eb52e7c,
0x2f022f80,0x2b5e2fe6,0x2b5e2fc9,0x230eaf46,0xacd826a1,0xaf30ad96,0xaf91a9f1,0x2c072fd4,0xad96affc,0x2fdd244e,0xa5dbaee9,0xaf5aad4d,0x2e7c217e,0xad722bb7,0x2fff2d00,0x2fc9217e,
0x2c5da934,0x2f5aa44e,0x30002cd8,0xaeb5adfe,0x2d722ff8,0xacb02d00,0xa7652d00,0x2fff28d5,0xaf02a515,0x217eaf80,0xaf1aaf46,0xaf022765,0xa814af5a,0x2b052fdd,0x2d4da5db,0x2c07ad96,
0xae5eafa0,0xa934aff4,0x2b05abb7,0xaee928d5,0x2eb51cb6,0x2d962ed0,0x2d962fe6,0x2c87ad72,0x27652f6e,0xaf80ac5d,0xaf46a5db,0xa5152f6e,0xaff4ad4d,0x2ff8244e,0xa17eaee9,0xa875affc,
0xad4d2875,0xafbc217e,0xacd8aff8,0x1fd92ff4,0xaa4eafe6,0x2e99aaaa,0x2fd42993,0xaa4eafc9,0x2fff2c87,0xacb02d96,0xa7652d96,0x2d722eb5,0xab5e2c07,0x2875af30,0xae3faf91,0xaf1aacd8,
0x2d962fbc,0x25db2ffc,0xafdda934,0x2f5a2c07,0xafc9a875,0xaaaaafa0,0x2993ad27,0xafe6a875,0x28d5ad72,0x2d002ed0,0x2d002fe6,0x2ff81cb6,0x2d4d2fd4,0xae5ead96,0xafeda9f1,0xaf9126a1,
0x2e1fa765,0x2ff49cb6,0xa8752ddc,0x2e1facb0,0x1fd92f5a,0xafbc25db,0xacd8afdd,0xad4d2d96,0xaeb5aee9,0x2f5aa934,0x30002b05,0x2c5dae5e,0x2f80230e,0xaed02b5e,0xacb02b5e,0xaaaa2f02,
0xacb0afd4,0x9cb6b000,0x2ddc2f5a,0xa765afd4,0x2ff42c07,0x217e2ffc,0xaff8a934,0x28752fbc,0xadfe28d5,0xa44eaff4,0x2cd8abb7,0xa934afa0,0x1648af46,0x25db2fe6,0x25db2fc9,0x29f12f80,
0xafff9648,0xae7ca6a1,0xafc9a6a1,0x2d722a4e,0x2ff81fd9,0x230e2ee9,0x2faf2814,0x217eaf91,0xafeda30e,0x2d4dafa0,0xaf91a8d5,0xae5e2f02,0x2fdd2515,0xb0002aaa,0x2f6e2993,0x2fdda765,
0xa30e2fff,0xad272fc9,0xad272e7c,0x2fafad72,0x2814afdd,0x2ffcaa4e,0x2dfeadba,0xae5ea5db,0xaa4e2f91,0xac5dac07,0xaeb52cd8,0x96482f30,0x2c32af1a,0xa9932ff4,0x2f46abb7,0x2e7caf1a,
0x2fdd1fd9,0x2dba2814,0x2a4e2ee9,0x25dbaf91,0xaf46a8d5,0x2765afaf,0xa515afaf,0xaf802e1f,0x2e3f2c32,0xafa02ddc,0xa17e2fff,0x2e3f2515,0xacd8adba,0x2dfe26a1,0x2934afd4,0x244eaf6e,
0x2814aff8,0x2dfeafaf,0x2ffca30e,0xae5ea17e,0xac872f46,0xaf5a2515,0xaf5aa765,0xa6a12f80,0x2e7cadba,0x1cb62e99,0x2ddc2c5d,0x2fc9adba,0xafaf2b05,0x2f1aaee9,0xab5eae5e,0xad00a934,
0xaf91a30e,0xacd8a8d5,0x2c07afa0,0xaf302f02,0x2dba2c32,0xac5d2fff,0xae992ddc,0x2dba2515,0xa993aeb5,0x2fc9a9f1,0x2fe6a9f1,0x2aaaafdd,0xa17e2fed,0xa30eadfe,0xafaf9fd9,0xaff82c07,
0xaa4e2fed,0xaeb52f91,0xac5dad4d,0x96482e5e,0x2e7cae3f,0x2ddc217e,0x1cb62fa0,0x2fc9ae3f,0xaff82993,0x2bb7afe6,0x2bb7afc9,0xab5eaaaa,0x2f3025db,0xafbc2a4e,0xaee92dba,0xadfe2fdd,
0x2f1a2515,0x2bb72993,0xaff42aaa,0x2f1aa765,0xab05adba,0x2e5eafd4,0x2ee926a1,0x2934af6e,0xa5db2fed,0xadba9fd9,0xaa4eadfe,0xafdd2c07,0x2ddcaf02,0xacb02ff8,0xa7652ff8,0x9cb62e3f,
0x2c32afdd,0x2f46af6e,0xa9933000,0x2e7cafdd,0xafaf2cd8,0xab5ea934,0x2f1aadfe,0xad00a44e,0x2f30217e,0xaee92faf,0xafbc230e,0xadfe2ff8,0xa9f1addc,0x2c5d2765,0x2c5d2cb0,0x2d961cb6,
0xa993aa4e,0x2765ac87,0xa515ac87,0xaaaa2dba,0xafa02f30,0xabb7244e,0xaff42e5e,0x28d51fd9,0x28142bb7,0xaf912e1f,0x1fd92d27,0x2ee9ad00,0x2fd4aed0,0xaf5a2fff,0x3000addc,0x2fd4afe6,
0xafaf2f46,0xafa02e7c,0xafa02c32,0x2d00a993,0x244e2c5d,0xaf913000,0xab052f5a,0x2fbcaeb5,0x3000adfe,0xac872e5e,0x2e99a814,0x2f6eaffc,0x2515ae1f,0x1cb62875,0x2d72aff4,0x2c32ae1f,
0x26a12b05,0xa9f12cd8,0xad962fed,0x2fd4affc,0x2fffae1f,0x2515230e,0x2c32230e,0x2ddcaf1a,0x2875ae7c,0x2d27aaaa,0x2fa0af80,0x2875ac32,0xaee929f1,0x2f91ae99,0x9fd9ac87,0xa8149648,
0x2fedaf1a,0x2f30ae3f,0x29342875,0x2814ab5e,0x26a1addc,0x3000afc9,0x3000ae7c,0xa5db9cb6,0xaed02a4e,0x2f46afd4,0x2993ae99,0xacb02a4e,0xae3f2ffc,0x2d27ae5e,0xae1f2814,0xaf022dfe,
0x9fd9abb7,0x2c07ad27,0x2fedae1f,0xadfe2d00,0xaf6e2cb0,0x25dba993,0x2c5daf46,0xaf6e2ed0,0xaddc2fdd,0xa5159648,0xac329648,0xafff2fd4,0x28d52814,0xabb72934,0xaff42f30,0xafa02fed,
0xb0002ee9,0xae992dfe,0x2c87af30,0xaf6e2fbc,0xac322f02,0xaf802f1a,0xaaaaa17e,0xae7c2f02,0x2b5e1cb6,0xaff42fc9,0xaff42e7c,0xad272ddc,0x2ffcaeb5,0xafed3000,0xacd82f5a,0xab052c5d,
0xa17e2c32,0xad002d72,0xabb71cb6,0xa17e2515,0x2dfea9f1,0xac072c87,0xafed2e99,0x1fd91648,0x2fd4afbc,0xa9f12b05,0xad962f91,0x26a1a44e,0x2aaaae3f,0xa76528d5,0x251528d5,0x2993a875,
0x2fe6aeb5,0x2ddcadba,0xafff2f6e,0x2ed0aeb5,0x2e3fafbc,0x2e1fadfe,0xad272f30,0x2f02aee9,0x1fd9ab5e,0x2e5eae3f,0x244e2875,0x2f30af1a,0xad962993,0x2e99ae7c,0x2e99ac32,0x2f5aaf46,
0x299329f1,0xa76525db,0x251525db,0x2aaa1648,0x28d52934,0xaf02acd8,0x230e244e,0x2fa02dfe,0x28142875,0xaf91aff8,0x1fd9217e,0x2ee92ff4,0x26a12765,0xaa4eaddc,0x16481cb6,0x26a12cb0,
0x2f022f46,0x2b5e2e7c,0x2b5e2c32,0x230ea993,0x2e5e2eb5,0xab051648,0x29342a4e,0x2ee92c5d,0x2d962dfe,0xafddae5e,0x25db2814,0x2f5a2ffc,0x2cb02d27,0xaddcafaf,0x1cb6230e,0x27652d27,
0x2fd42f91,0x2f6e2fed,0x2dba2e5e,0xa6a1ad4d,0x2fff2ff8,0x25152d00,0x2c322d00,0x2ddc28d5,0x2faf2fe6,0xae1fa993,0x28d52aaa,0x2faf2fc9,0x2ee92f5a,0xaf91afdd,0x1fd925db,0x28142d96,
0x2cd82b5e,0x2f912d00,0x2f302faf,0xac07af1a,0x2eb52ddc,0x2d962fc9,0x2d962e7c,0x2c871cb6,0x2fc92f5a,0xa99326a1,0x2aaa2c87,0x2fe62f5a,0x2ff42ffc,0xaff8ae5e,0x217e2814,0x28752dfe,
0x9fd9a875,0x2c07a17e,0x2fed2ff8,0xadfeaff4,0x29f12515,0x2fdd2f46,0x2eb52f80,0x29f1a765,0x2ddc2c87,0x25152d96,0x2c322d96,0x2fff2eb5,0x2fa02ee9,0xaf02ab05,0x230e2934,0x28d52e5e,
0xad96aee9,0xa5dbadfe,0x2fdd2f30,0xaf5aafbc,0xa765abb7,0x2f462b5e,0x2f802ff8,0x2515abb7,0x28d51cb6,0x2d002fc9,0x2d002e7c,0x2ff82ddc,0x2dfe2c5d,0xacd81648,0x244e2a4e,0x29342eb5,
0xaff8afc9,0xae3fafff,0x2f022d72,0xaff8ae7c,0xadfeaf5a,0x2c07a5db,0x2fed2fdd,0x9fd9ad96,0xa6a1ac07,0x2f6e2f91,0x2dba2f30,0x2fd42cd8,0x2aaa230e,0xa7652b5e,0x25152b5e,0x29932f02,
0xae7cac5d,0xafffad96,0x2d7229f1,0xafc9ac5d,0xaff4afbc,0xa17eadfe,0x2ff82f30,0xa875aee9,0xad4daf1a,0x2fed2d00,0x2e5e2faf,0x2f912b5e,0x1648a993,0x25db2e7c,0x25db2c32,0x29f12f46,
0xaddc9648,0xafe6a6a1,0xaed0a6a1,0x2fff2a4e,0xad27affc,0x2d00ac07,0xabb7afbc,0xae1f2934,0x2e5e230e,0x1fd92fa0,0x2f3028d5,0x244eaf02,0x2c872fe6,0xadbaaf46,0x2a4e2f80,0x2c872fc9,
0xa30e2d72,0xad272c32,0xad272515,0x2faf1cb6,0xafbcae99,0x1fd9af6e,0xad4db000,0xacd82c87,0x2a4eab05,0x2c5d2fbc,0x2eb5244e,0x1648af91,0x2ed02fa0,0xaf80ad00,0x2aaa2faf,0x2cb02fa0,
0x2c872ffc,0x16482fbc,0xa9f12c07,0x2e99a934,0xaf80a8d5,0xac32afaf,0xae7cafaf,0xaaaa2e1f,0xa30eaed0,0x2f1a2d72,0x2e1f9cb6,0xa30eafe6,0x2fed2dba,0xaffca6a1,0x2b052fd4,0x2cd82f6e,
0x2fbc2e1f,0x2d4d2f02,0x9fd92e3f,0x2cd8ad27,0xac872993,0xaf5aacb0,0xaf5aaed0,0xa6a12f46,0xacb0b000,0x2fff25db,0x2d72a6a1,0xa765b000,0x2faf2934,0xaf1a2814,0x2b5e2fed,0x2d002f30,
0x2f30230e,0x2fed28d5,0x28142fa0,0x2934af02,0x16482ed0,0xafd41cb6,0xafddad72,0x16482fe6,0xaf46aeb5,0x2ed0a9f1,0x2cb0a9f1,0xa993afdd,0x2e1fa44e,0xad002d4d,0x2bb72ffc,0x2d272ee9,
0x2a4eacd8,0x2eb5ab05,0x2c5d2ffc,0x1648afed,0x2cb02ff4,0xad722d27,0xafffab5e,0x27652ff4,0xaff8aaaa,0x2bb7ae7c,0x2bb7ac32,0xab5eaf80,0x2b05ac87,0xa8142f6e,0x2c073000,0x2d4d2e99,
0xa8d5afe6,0x2875af80,0x2e3f2f46,0xa8d5afc9,0x2f912dba,0xa44e2fd4,0xafbca6a1,0x2b052f6e,0xae99244e,0x9648affc,0x29f1ad4d,0xac87aee9,0x1cb6af02,0x25152ff8,0x2c322ff8,0x2d722e3f,
0xaed0ae99,0xaaaaaf5a,0x2f802d96,0xacb0ae99,0x2faf244e,0x2b5e2f30,0xaf1a1fd9,0x2d002e5e,0xab052d27,0xac07af02,0x2814ae3f,0xad4dae1f,0xa9f1afff,0x2c5d2ed0,0x2c5d2fe6,0x2d962ddc,
0xaf46aa4e,0xac32ac87,0xae7cac87,0x29932dba,0x2f1a2b05,0xa8752fed,0x2e3f2cd8,0x2b5eaffc,0xaee9abb7,0x2f30ae1f,0xadfead27,0xafbc2d00,0x2eb52c32,0xaf6e1cb6,0x2dba2d72,0x2eb52515,
0xafaf2993,0xafa02515,0xafa0a765,0x2d002aaa,0x2feda6a1,0x29342d96,0x2f3029f1,0x2814afd4,0xb0001fd9,0x2c87afed,0xae99ac07,0xaf6e2dfe,0x2fe6217e,0xafff2bb7,0x2ddc2d00,0x2ed0217e,
0xac5d2f30,0xaf5a2e5e,0xb000244e,0x2eb51fd9,0x2ddcae1f,0x2e7c230e,0x2fc9230e,0x1cb6af1a,0xaf022cb0,0x217eaf46,0xaf1aa993,0xaf022ed0,0x2fbca9f1,0xaf302e99,0x2dfe2c87,0x2ee91648,
0x244e2fa0,0xab052ff4,0xaf912bb7,0x2fbca8d5,0x26a1afff,0x3000ac32,0x3000a515,0xa5dbaddc,0xac322f6e,0xaaaaac5d,0xaf80a5db,0xae7c2f6e,0x2e3fadfe,0xad272fed,0x2e1f2c07,0x2f029fd9,
0x2dfe2bb7,0x28142d27,0xae5e2e1f,0x2ffcad00,0xaa4eae7c,0x2e99af80,0x2fd4aaaa,0xaa4eac32,0x9cb62fdd,0xae7c9648,0xafc99648,0xaddc2fd4,0x2b5eafbc,0xa8752f91,0x2e3f2b05,0x2f1aa44e,
0x3000a814,0x2e999fd9,0xac872f91,0x2f6eaee9,0xaed0a875,0x2993afa0,0x2f46ad27,0xacb0a875,0x2b5e2ddc,0xaff42c32,0xaff42515,0xad272fff,0x1fd9afd4,0x244e2d96,0x2e5e29f1,0x2f30a6a1,
0x2e1faed0,0x2ff4addc,0xa8752fff,0x2e1fafe6,0xaffc29f1,0xa814ac87,0x2e5eae99,0xadfe9648,0x2eb52814,0xaf5a2f30,0xb0002934,0xac5d2fed,0xa993ae3f,0x2c3228d5,0x2e7c28d5,0x2f46a875,
0x2515afd4,0x2d72b000,0x1cb62f5a,0x2c32afd4,0xae3f2ee9,0xae1f1fd9,0x2d27af91,0xaf022814,0x2ffca8d5,0xacd82ff4,0xafed2bb7,0xab052fa0,0xad96aaaa,0x2e99a515,0x2e992765,0x2f5aa993,
0x1cb6adba,0x2cb0aeb5,0x2765aeb5,0xaddc2f6e,0xaff82d4d,0xa30ea814,0xafaf2c07,0xa17e2b05,0xa44e2e3f,0xadfe2b5e,0xa9342f1a,0x2cd8a875,0x2fddacb0,0xb0002f80,0x2f6eaaaa,0x2fddaed0,
0xad009cb6,0xa17ea765,0xa17eacb0,0xabb72ddc,0xaee92fdd,0xad4d2a4e,0xaffc2dba,0x244e25db,0x29f12934,0xafd42ee9,0xa6a12e5e,0x2d96ab05,0x2fc9af1a,0xaf462ff4,0x2f80abb7,0x2fe6af1a,
0xafdd2d4d,0xadba2c07,0xaa4ea814,0xa5db2b05,0xaaaa2f1a,0xafc92f02,0xafe62f02,0x2993a17e,0x2e3fa765,0xafa02fff,0xa17e2d72,0x2e3facb0,0x2e5eb000,0xad4d2eb5,0x2f91ac5d,0x2fedaf5a,
0xaee92ff8,0xaffc2faf,0xad4d230e,0x244e217e,0x25db2aaa,0xaf6e2fe6,0xaf6e2fc9,0x2c5da993,0x2fe6adba,0xad722e99,0x1cb62c5d,0x2ed0adba,0x2bb7af30,0xa8d52c07,0x2fa0acd8,0x2ff4af91,
0xa9342e3f,0xae5e2f1a,0xaee92b5e,0x2b05a875,0x2dbaa765,0xac5d2d72,0xae992fff,0x2dbaacb0,0x2f80afd4,0xa7652a4e,0x25152a4e,0x2f46ae99,0x217eacd8,0x230e1fd9,0x2fafad4d,0x2ff8afbc,
0x29f1244e,0xa6a12934,0xafd42dfe,0x2d96acd8,0x2fe6ae3f,0x1cb6217e,0xad722fa0,0x2ed0ae3f,0x2d27af80,0x2875a515,0x28752765,0x2fa0af46,0xa934a5db,0x2c07aa4e,0x2fbcadba,0x2ffcafdd,
0x2f1aacb0,0x2bb7aaaa,0xaff42f80,0x2f1aaed0,0x2f30b000,0x2cd8ac5d,0xac072eb5,0x2f91af5a,0x25dbacd8,0x2dbaad4d,0x2a4e1fd9,0x2fddafbc,0xad722875,0x2e7cae1f,0x2fc9ae1f,0x2fffaff4,
0x2fc9afdd,0x2f80af6e,0xaf463000,0x2fe6afdd,0x2bb7ae5e,0x2fa0af91,0xa8d52d4d,0x2ff4afed,0xa934a17e,0x2fbcafaf,0x2c07a30e,0x2ffcaff8,0xaf5a2d72,0x2fd4afc9,0x2fd4ae7c,0x3000afff,
0x9d4d9e16,0xada6ae7d,0x9b769c84,0xabf0accf,0x985299e4,0xa897aa43,0x90b6957f,0xa102a5d8,0x13db0a48,0x242c1aad,0x191b1712,0x296d2783,0x1c201aad,0x2c632b1a,0x1db21ce9,0x2e112d3a,
0xa3f4a491,0xae51af42,0xa199a2c6,0xac70ad60,0x9e7ba06b,0xa922ab00,0x97129c20,0xa199a688,0x19e410b6,0x24aa1b76,0x1fa81d4d,0x2a112833,0x222f2102,0x2ce82bf0,0x2445235d,0x2ec92dd8,
0xa6a1a79c,0xaefcb004,0xa4aaa5a5,0xace8adf2,0xa166a35d,0xa9acabbe,0x99e49edf,0xa22fa738,0x1ce913db,0x25281c20,0x2262206b,0x2ab528a4,0x2528242c,0x2d6d2c63,0x271f2623,0x2f822e77,
0xa8a4a954,0xafa8b067,0xa688a7e8,0xad60ae84,0xa38fa528,0xaa37ac3d,0x9c20a0d0,0xa2c6a7e8,0x1edf157f,0x25a51c84,0x2478222f,0x2b592915,0x273825d8,0x2df22ccf,0x28fc284c,0x301d2f16,
0xa9f8aadb,0xb02ab0ca,0xa833a915,0xadd8af16,0xa4dca6a1,0xaac1ac9c,0x9d4da22f,0xa35da84c,0x206b1712,0x26231ce9,0x25bf23f4,0x2bfd2987,0x28a42783,0x2e772d3a,0x2a692987,0x307a2fb5,
0xab4cac31,0xb081b12e,0xa922aa37,0xae51afa8,0xa5f1a80d,0xab4cacfb,0x9e7ba38f,0xa3f4a8a4,0x21661852,0x26a11d4d,0x270524dc,0x2c5029f8,0x29ac2897,0x2efc2da6,0x2bd72ac1,0x30d7302a,
0xac50acf5,0xb0d7b192,0xaa11ab59,0xaec9b01d,0xa705a8ca,0xabd7ad5a,0x9fa8a478,0xa445a8fc,0x2262191b,0x271f1db2,0x282625bf,0x2ca22a69,0x2ab5296d,0x2f822e11,0x2ca22bfd,0x3135307a,
0xacfbadb9,0xb12eb1f7,0xab00ac3d,0xaf42b067,0xa80da987,0xac31adb9,0xa06ba528,0xa491a954,0x235d19e4,0x279c1e16,0x28ca26a1,0x2cf52adb,0x2bbe2a43,0x30042e7d,0x2d5a2c9c,0x319230ca,
0xb185b25c,0xb426b4cc,0xafbbb0b1,0xb1c6b306,0xac76ae18,0xaea3b08a,0xa4dca9ac,0xa738ac37,0x280d1e7b,0x2a0520d0,0x2d472b4c,0x2fdb2d6d,0x30472ee9,0x32663128,0x31f0311b,0x347933a8,
0xb1ddb2c1,0xb453b501,0xb01ab0fb,0xb204b352,0xacbcae77,0xaee9b0ba,0xa528aa05,0xa783ac63,0x284c1edf,0x2a432102,0x2d992bbe,0x30172da6,0x308a2f55,0x32aa315f,0x324f316b,0x34aa33fc,
0xb235b327,0xb481b537,0xb057b145,0xb242b39e,0xad01aed6,0xaf2fb0eb,0xa573aa5d,0xa7cfac90,0x288b1f44,0x2a822134,0x2deb2c18,0x30412ddf,0x30ce2fc2,0x32ef3196,0x32ae31bc,0x34db3428,
0xb28db38e,0xb4afb56d,0xb094b18f,0xb280b3eb,0xad47af36,0xaf75b11b,0xa5bfaab5,0xa80dacbc,0x28ca1fa8,0x2ac12166,0x2e3e2c50,0x306a2e18,0x31113017,0x333531cd,0x330d320e,0x350d3452,
0xb2e5b3f5,0xb4ddb5a3,0xb0d1b1da,0xb2beb41c,0xad8caf95,0xafbbb14b,0xa60aab0d,0xa833ace8,0x29092006,0x2b002199,0x2e902c89,0x30942e51,0x3155304d,0x337a3204,0x336d325f,0x3540347c,
0xb33eb42e,0xb50cb5da,0xb10eb224,0xb2fcb443,0xadd2aff5,0xb001b17c,0xa655ab65,0xa859ad14,0x29482039,0x2b4021cb,0x2ee32cc2,0x30be2e8a,0x31993084,0x33c0323b,0x33cd32b1,0x357234a6,
0xb398b463,0xb53ab612,0xb14bb26f,0xb33bb469,0xae18b02a,0xb024b1ac,0xa6a1abbe,0xa87ead40,0x2987206b,0x2b7f21fd,0x2f362cfb,0x30e72ec3,0x31dd30ba,0x34033273,0x34173303,0x35a534d1,
0xb3f2b497,0xb569b64a,0xb189b2bb,0xb37ab490,0xae5eb05a,0xb047b1dd,0xa6ecac0b,0xa8a4ad6d,0x29c6209d,0x2bbe222f,0x2f882d34,0x31112efc,0x322130f1,0x342632aa,0x34483356,0x35d934fc,
0xb599b682,0xb722b82e,0xb3b9b4b7,0xb4ddb5f9,0xb06ab20e,0xb185b398,0xa8caad99,0xa9f8aefc,0x2bfd2262,0x2cfb23f4,0x313b2f36,0x328d3081,0x344932e2,0x35693453,0x360d3527,0x37bd368b,
0xb5c9b6bb,0xb755b84d,0xb3f8b4df,0xb4feb622,0xb08db23e,0xb1a9b3ca,0xa8f0adc5,0xaa1eaf29,0x2c1e2294,0x2d1b2413,0x31652f6f,0x32b7309d,0x346d331a,0x358e3470,0x36413553,0x37f536ba,
0xb5f9b6f5,0xb789b86d,0xb41cb506,0xb51fb64c,0xb0b1b26f,0xb1cdb3fc,0xa915adf2,0xaa43af55,0x2c3d22c6,0x2d3a242c,0x318f2fa8,0x32e230ba,0x34903352,0x35b3348d,0x3676357e,0x381736e8,
0xb629b72f,0xb7bdb88d,0xb43cb52e,0xb540b676,0xb0d4b2a1,0xb1f0b417,0xa93bae1e,0xaa69af82,0x2c5d22f9,0x2d5a2445,0x31b92fe2,0x330d30d7,0x34b4338b,0x35d934aa,0x36ab35ab,0x38343717,
0xb65ab76a,0xb7f1b8ad,0xb45cb556,0xb561b6a0,0xb0f7b2d2,0xb214b430,0xa961ae4b,0xaa8fafaf,0x2c7d232b,0x2d79245f,0x31e3300e,0x333830f4,0x34d833c3,0x35fe34c7,0x36e035d7,0x38513746,
0xb68bb7a5,0xb813b8ce,0xb47cb57e,0xb582b6ca,0xb11bb303,0xb238b449,0xa987ae77,0xaab5afdb,0x2c9c235d,0x2d992478,0x320e302a,0x33633111,0x34fc33fc,0x362434e4,0x37173604,0x386f3775,
0xb6bdb7e2,0xb82eb8f0,0xb49cb5a7,0xb5a3b6f5,0xb13eb335,0xb25cb463,0xa9acaea3,0xaadbb004,0x2cbc238f,0x2db92491,0x32383047,0x338e312e,0x3520341a,0x364a3501,0x374d3631,0x388d37a5,
0xb6efb80f,0xb849b911,0xb4bdb5d0,0xb5c5b720,0xb162b366,0xb280b47c,0xa9d2aed0,0xab00b01a,0x2cdb23c2,0x2dd824aa,0x32623064,0x33b9314b,0x35453437,0x3670351f,0x3785365e,0x38ab37d6,
0xb865b934,0xb94dba5c,0xb5e7b74c,0xb6fcb85a,0xb2a4b495,0xb3c6b564,0xab26b031,0xac2bb0e4,0x2df824c3,0x2ef6258c,0x33e43168,0x34a13252,0x3697353c,0x37d4362d,0x38ca3803,0x39d038d0,
0xb880b957,0xb96bba84,0xb609b777,0xb720b872,0xb2c8b4af,0xb3ebb57e,0xab4cb047,0xac3db0fb,0x2e1824dc,0x2f1625a5,0x34083185,0x34b7326f,0x36bd355a,0x37fd364c,0x38e9381c,0x39f338eb,
0xb89cb97a,0xb98abaad,0xb62bb7a4,0xb744b88a,0xb2ecb4c9,0xb408b599,0xab72b05d,0xac50b111,0x2e3724f5,0x2f3625bf,0x341e31a2,0x34ce328d,0x36e43577,0x3813366b,0x39093835,0x3a173906,
0xb8b9b99e,0xb9aabad7,0xb64db7d0,0xb768b8a2,0xb310b4e2,0xb41ab5b3,0xab98b074,0xac63b128,0x2e57250f,0x2f5525d8,0x343331c0,0x34e432aa,0x370b3595,0x3828368a,0x3929384e,0x3a3b3922,
0xb8d6b9c3,0xb9cabb02,0xb670b7fd,0xb78cb8ba,0xb335b4fc,0xb42db5ce,0xabbeb08a,0xac76b13e,0x2e772528,0x2f7525f1,0x344931dd,0x34fa32c8,0x373335b3,0x383d36a9,0x39493868,0x3a60393e,
0xb8f3b9e8,0xb9ebbb2d,0xb693b815,0xb7b1b8d2,0xb359b516,0xb43fb5e9,0xabe3b0a1,0xac89b155,0x2e972541,0x2f95260a,0x345f31fa,0x351132e5,0x375b35d2,0x385236c8,0x396a3881,0x3a86395a,
0xb910ba0e,0xba0cbb59,0xb6b6b82c,0xb7d6b8eb,0xb37db530,0xb452b604,0xac05b0b7,0xac9cb16b,0x2eb6255a,0x2fb52623,0x34753217,0x35273303,0x378335f0,0x386836e8,0x398c389b,0x3aac3977,
0xb92eba35,0xba2dbb87,0xb6d9b843,0xb7fbb904,0xb3a2b54a,0xb464b61e,0xac18b0ce,0xacafb182,0x2ed62573,0x2fd5263c,0x348b3235,0x353e3321,0x37ab360e,0x387d3708,0x39ae38b6,0x3ad33994,
0x9ce99db2,0xad3aae11,0x9aad9c20,0xab1aac63,0x9712991b,0xa783a96d,0x8a4893db,0x9aada42c,0x157f10b6,0x25d82102,0x19e41852,0x2a432897,0x1c841b76,0x2ccf2bf0,0x1e161d4d,0x2e7d2da6,
0xa35da445,0xadd8aec9,0xa102a22f,0xabf0ace8,0x9d4d9fa8,0xa833aa11,0x90b699e4,0x9b76a4aa,0x1c201712,0x26882199,0x206b1e7b,0x2b002922,0x22c62199,0x2d602c70,0x249123f4,0x2f422e51,
0xa623a71f,0xae77af82,0xa42ca528,0xac63ad6d,0xa06ba262,0xa8a4aab5,0x93db9ce9,0x9c20a528,0x1edf19e4,0x2738222f,0x235d2166,0x2bbe29ac,0x25a524aa,0x2df22ce8,0x279c26a1,0x30042efc,
0xa84ca8fc,0xaf16b01d,0xa5d8a738,0xaccfadf2,0xa22fa478,0xa915ab59,0x957f9edf,0x9c84a5a5,0x20d01c20,0x27e822c6,0x2528238f,0x2c3d2a37,0x27e82688,0x2e842d60,0x295428a4,0x30672fa8,
0xa987aa69,0xafb5b07a,0xa783a8a4,0xad3aae77,0xa3f4a5bf,0xa987abfd,0x9712a06b,0x9ce9a623,0x222f1d4d,0x284c235d,0x26a124dc,0x2c9c2ac1,0x29152833,0x2f162dd8,0x2adb29f8,0x30ca302a,
0xaac1abd7,0xb02ab0d7,0xa897a9ac,0xada6aefc,0xa4dca705,0xa9f8ac50,0x9852a166,0x9d4da6a1,0x238f1e7b,0x28a423f4,0x280d25f1,0x2cfb2b4c,0x2a372922,0x2fa82e51,0x2c312b4c,0x312e3081,
0xabfdaca2,0xb07ab135,0xa96daab5,0xae11af82,0xa5bfa826,0xaa69aca2,0x991ba262,0x9db2a71f,0x24781fa8,0x28fc2445,0x28ca2705,0x2d5a2bd7,0x2b592a11,0x301d2ec9,0x2cf52c50,0x319230d7,
0xac9cad5a,0xb0cab192,0xaa43abbe,0xae7db004,0xa6a1a8ca,0xaadbacf5,0x99e4a35d,0x9e16a79c,0x2528206b,0x29542491,0x2987280d,0x2db92c31,0x2c3d2b00,0x30672f42,0x2db92cfb,0x31f7312e,
0xb11bb1f0,0xb3a8b479,0xaee9b047,0xb128b266,0xab4cad47,0xad6dafdb,0x9e7ba80d,0xa0d0aa05,0x29ac24dc,0x2c372738,0x2e182c76,0x308a2ea3,0x30b12fbb,0x330631c6,0x325c3185,0x34cc3426,
0xb16bb24f,0xb3fcb4aa,0xaf55b08a,0xb15fb2aa,0xabbead99,0xada6b017,0x9edfa84c,0xa102aa43,0x2a052528,0x2c632783,0x2e772cbc,0x30ba2ee9,0x30fb301a,0x33523204,0x32c131dd,0x35013453,
0xb1bcb2ae,0xb428b4db,0xafc2b0ce,0xb196b2ef,0xac18adeb,0xaddfb041,0x9f44a88b,0xa134aa82,0x2a5d2573,0x2c9027cf,0x2ed62d01,0x30eb2f2f,0x31453057,0x339e3242,0x33273235,0x35373481,
0xb20eb30d,0xb452b50d,0xb017b111,0xb1cdb335,0xac50ae3e,0xae18b06a,0x9fa8a8ca,0xa166aac1,0x2ab525bf,0x2cbc280d,0x2f362d47,0x311b2f75,0x318f3094,0x33eb3280,0x338e328d,0x356d34af,
0xb25fb36d,0xb47cb540,0xb04db155,0xb204b37a,0xac89ae90,0xae51b094,0xa006a909,0xa199ab00,0x2b0d260a,0x2ce82833,0x2f952d8c,0x314b2fbb,0x31da30d1,0x341c32be,0x33f532e5,0x35a334dd,
0xb2b1b3cd,0xb4a6b572,0xb084b199,0xb23bb3c0,0xacc2aee3,0xae8ab0be,0xa039a948,0xa1cbab40,0x2b652655,0x2d142859,0x2ff52dd2,0x317c3001,0x3224310e,0x344332fc,0x342e333e,0x35da350c,
0xb303b417,0xb4d1b5a5,0xb0bab1dd,0xb273b403,0xacfbaf36,0xaec3b0e7,0xa06ba987,0xa1fdab7f,0x2bbe26a1,0x2d40287e,0x302a2e18,0x31ac3024,0x326f314b,0x3469333b,0x34633398,0x3612353a,
0xb356b448,0xb4fcb5d9,0xb0f1b221,0xb2aab426,0xad34af88,0xaefcb111,0xa09da9c6,0xa22fabbe,0x2c0b26ec,0x2d6d28a4,0x305a2e5e,0x31dd3047,0x32bb3189,0x3490337a,0x349733f2,0x364a3569,
0xb527b60d,0xb68bb7bd,0xb2e2b449,0xb453b569,0xaf36b13b,0xb081b28d,0xa262abfd,0xa3f4acfb,0x2d9928ca,0x2efc29f8,0x320e306a,0x33983185,0x34b733b9,0x35f934dd,0x36823599,0x382e3722,
0xb553b641,0xb6bab7f5,0xb31ab46d,0xb470b58e,0xaf6fb165,0xb09db2b7,0xa294ac1e,0xa413ad1b,0x2dc528f0,0x2f292a1e,0x323e308d,0x33ca31a9,0x34df33f8,0x362234fe,0x36bb35c9,0x384d3755,
0xb57eb676,0xb6e8b817,0xb352b490,0xb48db5b3,0xafa8b18f,0xb0bab2e2,0xa2c6ac3d,0xa42cad3a,0x2df22915,0x2f552a43,0x326f30b1,0x33fc31cd,0x3506341c,0x364c351f,0x36f535f9,0x386d3789,
0xb5abb6ab,0xb717b834,0xb38bb4b4,0xb4aab5d9,0xafe2b1b9,0xb0d7b30d,0xa2f9ac5d,0xa445ad5a,0x2e1e293b,0x2f822a69,0x32a130d4,0x341731f0,0x352e343c,0x36763540,0x372f3629,0x388d37bd,
0xb5d7b6e0,0xb746b851,0xb3c3b4d8,0xb4c7b5fe,0xb00eb1e3,0xb0f4b338,0xa32bac7d,0xa45fad79,0x2e4b2961,0x2faf2a8f,0x32d230f7,0x34303214,0x3556345c,0x36a03561,0x376a365a,0x38ad37f1,
0xb604b717,0xb775b86f,0xb3fcb4fc,0xb4e4b624,0xb02ab20e,0xb111b363,0xa35dac9c,0xa478ad99,0x2e772987,0x2fdb2ab5,0x3303311b,0x34493238,0x357e347c,0x36ca3582,0x37a5368b,0x38ce3813,
0xb631b74d,0xb7a5b88d,0xb41ab520,0xb501b64a,0xb047b238,0xb12eb38e,0xa38facbc,0xa491adb9,0x2ea329ac,0x30042adb,0x3335313e,0x3463325c,0x35a7349c,0x36f535a3,0x37e236bd,0x38f0382e,
0xb65eb785,0xb7d6b8ab,0xb437b545,0xb51fb670,0xb064b262,0xb14bb3b9,0xa3c2acdb,0xa4aaadd8,0x2ed029d2,0x301a2b00,0x33663162,0x347c3280,0x35d034bd,0x372035c5,0x380f36ef,0x39113849,
0xb803b8ca,0xb8d0b9d0,0xb53cb697,0xb62db7d4,0xb168b3e4,0xb252b4a1,0xa4c3adf8,0xa58caef6,0x30312b26,0x30e42c2b,0x349532a4,0x356433c6,0x374c35e7,0x385a36fc,0x39343865,0x3a5c394d,
0xb81cb8e9,0xb8ebb9f3,0xb55ab6bd,0xb64cb7fd,0xb185b408,0xb26fb4b7,0xa4dcae18,0xa5a5af16,0x30472b4c,0x30fb2c3d,0x34af32c8,0x357e33eb,0x37773609,0x38723720,0x39573880,0x3a84396b,
0xb835b909,0xb906ba17,0xb577b6e4,0xb66bb813,0xb1a2b41e,0xb28db4ce,0xa4f5ae37,0xa5bfaf36,0x305d2b72,0x31112c50,0x34c932ec,0x35993408,0x37a4362b,0x388a3744,0x397a389c,0x3aad398a,
0xb84eb929,0xb922ba3b,0xb595b70b,0xb68ab828,0xb1c0b433,0xb2aab4e4,0xa50fae57,0xa5d8af55,0x30742b98,0x31282c63,0x34e23310,0x35b3341a,0x37d0364d,0x38a23768,0x399e38b9,0x3ad739aa,
0xb868b949,0xb93eba60,0xb5b3b733,0xb6a9b83d,0xb1ddb449,0xb2c8b4fa,0xa528ae77,0xa5f1af75,0x308a2bbe,0x313e2c76,0x34fc3335,0x35ce342d,0x37fd3670,0x38ba378c,0x39c338d6,0x3b0239ca,
0xb881b96a,0xb95aba86,0xb5d2b75b,0xb6c8b852,0xb1fab45f,0xb2e5b511,0xa541ae97,0xa60aaf95,0x30a12be3,0x31552c89,0x35163359,0x35e9343f,0x38153693,0x38d237b1,0x39e838f3,0x3b2d39eb,
0xb89bb98c,0xb977baac,0xb5f0b783,0xb6e8b868,0xb217b475,0xb303b527,0xa55aaeb6,0xa623afb5,0x30b72c05,0x316b2c9c,0x3530337d,0x36043452,0x382c36b6,0x38eb37d6,0x3a0e3910,0x3b593a0c,
0xb8b6b9ae,0xb994bad3,0xb60eb7ab,0xb708b87d,0xb235b48b,0xb321b53e,0xa573aed6,0xa63cafd5,0x30ce2c18,0x31822caf,0x354a33a2,0x361e3464,0x384336d9,0x390437fb,0x3a35392e,0x3b873a2d,
0x214d2216,0x319b326c,0x1f762084,0x2fe830c8,0x1c521de4,0x2c962e40,0x14b6197f,0x250229d7,0x97db8e48,0xa82c9ead,0x9d1b9b12,0xad6bab82,0xa0209ead,0xb05eaf14,0xa1b2a0e9,0xb204b131,
0x27f32890,0x3241332b,0x259826c6,0x306a3156,0x227b246b,0x2d202efb,0x1b122020,0x25982a87,0x9de494b6,0xa8aa9f76,0xa3a8a14d,0xae0eac32,0xa62fa502,0xb0e1afe8,0xa845a75d,0xb2b6b1cc,
0x2aa02b9b,0x32e733e8,0x28aa29a5,0x30e131e5,0x2566275d,0x2daa2fb6,0x1de422df,0x262f2b36,0xa0e997db,0xa927a020,0xa661a46b,0xaeb0aca2,0xa927a82c,0xb163b05e,0xab1daa22,0xb368b266,
0x2ca22d52,0x338d3452,0x2a872be6,0x31563273,0x278f2927,0x2e333039,0x202024cf,0x26c62be6,0xa2df997f,0xa9a5a084,0xa877a62f,0xaf53ad13,0xab36a9d7,0xb1e5b0c8,0xacfaac4b,0xb40cb300,
0x2df52ed6,0x341834b0,0x2c322d13,0x31cc3300,0x28dc2aa0,0x2ebd3096,0x214d262f,0x275d2c4b,0xa46b9b12,0xaa22a0e9,0xa9bea7f3,0xaff5ad84,0xaca2ab82,0xb266b131,0xae65ad84,0xb464b399,
0x2f46302c,0x346a350c,0x2d202e33,0x3241338d,0x29f02c0c,0x2f4630f3,0x227b278f,0x27f32ca2,0xa5669c52,0xaaa0a14d,0xab04a8dc,0xb04badf5,0xadaaac96,0xb2e7b19b,0xafcfaebd,0xb4bcb418,
0x304b30ed,0x34bc3568,0x2e0e2f53,0x32b6340c,0x2b042cc8,0x2fcf3150,0x23a82877,0x28452cfa,0xa6619d1b,0xab1da1b2,0xac25a9be,0xb09cae65,0xaeb0ad6b,0xb368b204,0xb09caff5,0xb512b464,
0x30f331ad,0x350c35c4,0x2efb3039,0x332b3452,0x2c0c2d84,0x302c31ad,0x246b2927,0x28902d52,0xa75d9de4,0xab9ba216,0xacc8aaa0,0xb0edaed6,0xafb6ae40,0xb3e8b26c,0xb150b096,0xb568b4b0,
0x355d361e,0x37c63867,0x339f3497,0x359836b4,0x3071320a,0x32913473,0x28dc2daa,0x2b363032,0xac0ca27b,0xae01a4cf,0xb13eaf46,0xb3bdb163,0xb434b2d5,0xb627b506,0xb5beb4fa,0xb826b73e,
0x35ac3678,0x3808388f,0x340934dd,0x35cf36f5,0x30b53266,0x32d534a0,0x29272e01,0x2b82305e,0xac4ba2df,0xae40a502,0xb18eafb6,0xb406b19b,0xb473b33d,0xb663b539,0xb612b545,0xb84cb784,
0x35fb36d0,0x382c38b7,0x34433521,0x36073736,0x30f932c2,0x331834ce,0x29722e59,0x2bcd308a,0xac89a344,0xae7ea534,0xb1dfb013,0xb42eb1d2,0xb4b3b3a5,0xb6a0b56b,0xb666b58f,0xb872b7c9,
0x36493728,0x385038de,0x347c3565,0x363e3776,0x313e331e,0x335c34fa,0x29be2eb0,0x2c0c30b5,0xacc8a3a8,0xaebda566,0xb22fb04b,0xb455b20a,0xb4f1b406,0xb6dcb59d,0xb6b9b5d8,0xb898b807,
0x3697377e,0x38743904,0x34b635a9,0x367537b6,0x3182337a,0x339f3527,0x2a092f08,0x2c3230e1,0xad07a406,0xaefba598,0xb27fb083,0xb47cb241,0xb530b43a,0xb717b5cf,0xb70cb621,0xb8bdb828,
0x36e437d4,0x3897392a,0x34ee35ed,0x36ab37f5,0x31c633d6,0x33e23554,0x2a542f5f,0x2c57310c,0xad45a439,0xaf3aa5cb,0xb2cfb0bb,0xb4a4b279,0xb56eb46d,0xb752b601,0xb75db669,0xb8e1b84a,
0x37303814,0x38b9394e,0x3527362f,0x36e1381a,0x320a3418,0x34123580,0x2aa02fb6,0x2c7d3137,0xad84a46b,0xaf78a5fd,0xb31eb0f3,0xb4cbb2b0,0xb5acb4a0,0xb78cb632,0xb7adb6b1,0xb905b86b,
0x377c383e,0x38db3972,0x355f3672,0x37173838,0x324e3446,0x343435ac,0x2aeb3007,0x2ca23163,0xadc3a49d,0xafb6a62f,0xb36eb12b,0xb4f1b2e7,0xb5eab4d4,0xb7c6b663,0xb7fdb6f8,0xb928b88b,
0x38fd3996,0x39f33a91,0x374c3857,0x3874393e,0x345535d8,0x355d3730,0x2cc8318e,0x2df532e7,0xaff5a661,0xb0f3a7f3,0xb518b31e,0xb649b46a,0xb800b694,0xb8dbb808,0xb94bb8ab,0xba45b99b,
0x391e39b8,0x3a0f3aad,0x37813875,0x388c3959,0x34763604,0x357d375a,0x2cee31b9,0x2e1a3312,0xb01aa694,0xb112a813,0xb53fb356,0xb66fb485,0xb81cb6c5,0xb8f5b81f,0xb96db8cb,0xba61b9b7,
0x393e39da,0x3a2b3ac7,0x37b63893,0x38a53974,0x3497362f,0x359d3784,0x2d1331e5,0x2e40333d,0xb039a6c6,0xb131a82c,0xb565b38d,0xb694b4a0,0xb838b6f5,0xb90fb836,0xb98eb8ea,0xba7cb9d2,
0x395e39fb,0x3a453ae0,0x37ea38b0,0x38bd398e,0x34b9365b,0x35be37ad,0x2d393210,0x2e653368,0xb058a6f8,0xb150a845,0xb58cb3c3,0xb6b9b4bc,0xb854b725,0xb928b84c,0xb9aeb909,0xba97b9ed,
0x397d3a1b,0x3a5f3af9,0x380f38cd,0x38d539a8,0x34da3686,0x35de37d7,0x2d5e323b,0x2e8b3393,0xb077a72a,0xb16fa85e,0xb5b2b3fa,0xb6deb4d7,0xb870b755,0xb941b863,0xb9ceb927,0xbab0ba07,
0x399b3a3a,0x3a793b10,0x382838ea,0x38ed39c1,0x34fa36b1,0x35fe3800,0x2d843266,0x2eb033bd,0xb096a75d,0xb18ea877,0xb5d8b418,0xb703b4f1,0xb88bb784,0xb95ab879,0xb9edb945,0xbac9ba21,
0x39b93a58,0x3a913b26,0x38423906,0x390439da,0x351b36dc,0x361e3814,0x2daa3291,0x2ed633e8,0xb0b5a78f,0xb1ada890,0xb5feb434,0xb728b50c,0xb8a6b7b3,0xb972b88f,0xba0bb962,0xbae0ba3a,
0x39d73a75,0x3aa93b3c,0x385b3922,0x391b39f2,0x353c3706,0x363e3828,0x2dcf32bc,0x2efb3409,0xb0d4a7c1,0xb1cca8aa,0xb624b44f,0xb74cb527,0xb8c1b7e2,0xb98ab8a5,0xba29b97f,0xbaf7ba52,
0x3ac03b50,0x3b5e3bcb,0x39323a0a,0x39de3ab8,0x365e383c,0x375738d7,0x2f21341f,0x302634c8,0xb1eba8c3,0xb2e1a98c,0xb770b542,0xb846b615,0xb9a2b8bb,0xba51b960,0xbb0dba6a,0xbb9cbb11,
0x3ad73b63,0x3b6e3bd6,0x39493a22,0x39f23acb,0x367d3850,0x377638ea,0x2f463434,0x303934dd,0xb20aa8dc,0xb300a9a5,0xb795b55d,0xb857b62f,0xb9b9b8d0,0xba65b974,0xbb22ba81,0xbba9bb24,
0x3aec3b75,0x3b7d3bdf,0x395f3a39,0x3a063ade,0x369d3864,0x379538fd,0x2f6c3449,0x304b34f1,0xb229a8f5,0xb31ea9be,0xb7b8b577,0xb868b649,0xb9d0b8e5,0xba79b987,0xbb36ba97,0xbbb6bb35,
0x3b013b86,0x3b8c3be7,0x39753a4f,0x3a193af0,0x36bc3878,0x37b3390f,0x2f91345e,0x305e3506,0xb247a90e,0xb33da9d7,0xb7dcb592,0xb879b663,0xb9e7b8fa,0xba8cb99a,0xbb4abaad,0xbbc2bb46,
0x3b153b96,0x3b993bee,0x398a3a65,0x3a2d3b02,0x36dc388b,0x37d13921,0x2fb63473,0x3071351b,0xb266a927,0xb35ca9f0,0xb800b5ac,0xb88ab67d,0xb9fdb90f,0xba9fb9ad,0xbb5cbac3,0xbbccbb56,
0x3b283ba5,0x3ba63bf4,0x39a03a7a,0x3a3f3b13,0x36fb389e,0x37ef3933,0x2fdc3488,0x30833530,0xb285a940,0xb37aaa09,0xb811b5c7,0xb89bb697,0xba12b924,0xbab1b9c0,0xbb6dbad7,0xbbd6bb65,
0x3b3b3bb3,0x3bb23bf9,0x39b53a8f,0x3a523b24,0x371a38b2,0x38073945,0x3001349d,0x30963545,0xb2a4a959,0xb399aa22,0xb823b5e1,0xb8abb6b1,0xba28b938,0xbac3b9d2,0xbb7ebaeb,0xbbdfbb74,
0x3b4d3bc0,0x3bbd3bfc,0x39ca3aa4,0x3a643b34,0x373938c5,0x38153957,0x301334b3,0x30a9355a,0xb2c2a972,0xb3b7aa3b,0xb834b5fb,0xb8bcb6ca,0xba3cb94c,0xbad4b9e4,0xbb8dbaff,0xbbe6bb82,
0x20e921b2,0x31313204,0x1ead2020,0x2f14305e,0x1b121d1b,0x2b822d6b,0xe4817db,0x1ead282c,0x997f94b6,0xa9d7a502,0x9de49c52,0xae40ac96,0xa0849f76,0xb0c8afe8,0xa216a14d,0xb26cb19b,
0x275d2845,0x31cc32b6,0x2502262f,0x2fe830e1,0x214d23a8,0x2c322e0e,0x14b61de4,0x1f7628aa,0xa0209b12,0xaa87a598,0xa46ba27b,0xaefbad20,0xa6c6a598,0xb156b06a,0xa890a7f3,0xb32bb241,
0x2a222b1d,0x32663368,0x282c2927,0x305e3163,0x246b2661,0x2ca22eb0,0x17db20e9,0x20202927,0xa2df9de4,0xab36a62f,0xa75da566,0xafb6adaa,0xa9a5a8aa,0xb1e5b0e1,0xab9baaa0,0xb3e8b2e7,
0x2c4b2cfa,0x3300340c,0x29d72b36,0x30c831e5,0x262f2877,0x2d132f53,0x197f22df,0x208429a5,0xa4cfa020,0xabe6a6c6,0xa927a78f,0xb039ae33,0xabe6aa87,0xb273b156,0xad52aca2,0xb452b38d,
0x2d842e65,0x33993464,0x2b822ca2,0x31313266,0x27f329be,0x2d842ff5,0x1b12246b,0x20e92a22,0xa62fa14d,0xac4ba75d,0xaaa0a8dc,0xb096aebd,0xad13ac32,0xb300b1cc,0xaed6adf5,0xb4b0b418,
0x2ebd2fcf,0x341834bc,0x2c962daa,0x319b32e7,0x28dc2b04,0x2df5304b,0x1c522566,0x214d2aa0,0xa78fa27b,0xaca2a7f3,0xac0ca9f0,0xb0f3af46,0xae33ad20,0xb38db241,0xb02caf46,0xb50cb46a,
0x2ff5309c,0x34643512,0x2d6b2eb0,0x32043368,0x29be2c25,0x2e65309c,0x1d1b2661,0x21b22b1d,0xa877a3a8,0xacfaa845,0xacc8ab04,0xb150afcf,0xaf53ae0e,0xb40cb2b6,0xb0edb04b,0xb568b4bc,
0x30963150,0x34b03568,0x2e402fb6,0x326c33e8,0x2aa02cc8,0x2ed630ed,0x1de4275d,0x22162b9b,0xa927a46b,0xad52a890,0xad84ac0c,0xb1adb02c,0xb039aefb,0xb452b32b,0xb1adb0f3,0xb5c4b50c,
0x34fa35be,0x373e3826,0x32d53434,0x35063627,0x2f46313e,0x316333bd,0x227b2c0c,0x24cf2e01,0xadaaa8dc,0xb032ab36,0xb20ab071,0xb473b291,0xb497b39f,0xb6b4b598,0xb61eb55d,0xb867b7c6,
0x35453612,0x3784384c,0x333d3473,0x35393663,0x2fb6318e,0x319b3406,0x22df2c4b,0x25022e40,0xae01a927,0xb05eab82,0xb266b0b5,0xb4a0b2d5,0xb4ddb409,0xb6f5b5cf,0xb678b5ac,0xb88fb808,
0x358f3666,0x37c93872,0x33a534b3,0x356b36a0,0x301331df,0x31d2342e,0x23442c89,0x25342e7e,0xae59a972,0xb08aabcd,0xb2c2b0f9,0xb4ceb318,0xb521b443,0xb736b607,0xb6d0b5fb,0xb8b7b82c,
0x35d836b9,0x38073898,0x340634f1,0x359d36dc,0x304b322f,0x320a3455,0x23a82cc8,0x25662ebd,0xaeb0a9be,0xb0b5ac0c,0xb31eb13e,0xb4fab35c,0xb565b47c,0xb776b63e,0xb728b649,0xb8deb850,
0x3621370c,0x382838bd,0x343a3530,0x35cf3717,0x3083327f,0x3241347c,0x24062d07,0x25982efb,0xaf08aa09,0xb0e1ac32,0xb37ab182,0xb527b39f,0xb5a9b4b6,0xb7b6b675,0xb77eb697,0xb904b874,
0x3669375d,0x384a38e1,0x346d356e,0x36013752,0x30bb32cf,0x327934a4,0x24392d45,0x25cb2f3a,0xaf5faa54,0xb10cac57,0xb3d6b1c6,0xb554b3e2,0xb5edb4ee,0xb7f5b6ab,0xb7d4b6e4,0xb92ab897,
0x36b137ad,0x386b3905,0x34a035ac,0x3632378c,0x30f3331e,0x32b034cb,0x246b2d84,0x25fd2f78,0xafb6aaa0,0xb137ac7d,0xb418b20a,0xb580b412,0xb62fb527,0xb81ab6e1,0xb814b730,0xb94eb8b9,
0x36f837fd,0x388b3928,0x34d435ea,0x366337c6,0x312b336e,0x32e734f1,0x249d2dc3,0x262f2fb6,0xb007aaeb,0xb163aca2,0xb446b24e,0xb5acb434,0xb672b55f,0xb838b717,0xb83eb77c,0xb972b8db,
0x38ab394b,0x399b3a45,0x36943800,0x380838db,0x331e3518,0x346a3649,0x26612ff5,0x27f330f3,0xb18eacc8,0xb2e7adf5,0xb5d8b455,0xb730b55d,0xb857b74c,0xb93eb874,0xb996b8fd,0xba91b9f3,
0x38cb396d,0x39b73a61,0x36c5381c,0x381f38f5,0x3356353f,0x3485366f,0x2694301a,0x28133112,0xb1b9acee,0xb312ae1a,0xb604b476,0xb75ab57d,0xb875b781,0xb959b88c,0xb9b8b91e,0xbaadba0f,
0x38ea398e,0x39d23a7c,0x36f53838,0x3836390f,0x338d3565,0x34a03694,0x26c63039,0x282c3131,0xb1e5ad13,0xb33dae40,0xb62fb497,0xb784b59d,0xb893b7b6,0xb974b8a5,0xb9dab93e,0xbac7ba2b,
0x390939ae,0x39ed3a97,0x37253854,0x384c3928,0x33c3358c,0x34bc36b9,0x26f83058,0x28453150,0xb210ad39,0xb368ae65,0xb65bb4b9,0xb7adb5be,0xb8b0b7ea,0xb98eb8bd,0xb9fbb95e,0xbae0ba45,
0x392739ce,0x3a073ab0,0x37553870,0x38633941,0x33fa35b2,0x34d736de,0x272a3077,0x285e316f,0xb23bad5e,0xb393ae8b,0xb686b4da,0xb7d7b5de,0xb8cdb80f,0xb9a8b8d5,0xba1bb97d,0xbaf9ba5f,
0x394539ed,0x3a213ac9,0x3784388b,0x3879395a,0x341835d8,0x34f13703,0x275d3096,0x2877318e,0xb266ad84,0xb3bdaeb0,0xb6b1b4fa,0xb800b5fe,0xb8eab828,0xb9c1b8ed,0xba3ab99b,0xbb10ba79,
0x39623a0b,0x3a3a3ae0,0x37b338a6,0x388f3972,0x343435fe,0x350c3728,0x278f30b5,0x289031ad,0xb291adaa,0xb3e8aed6,0xb6dcb51b,0xb814b61e,0xb906b842,0xb9dab904,0xba58b9b9,0xbb26ba91,
0x397f3a29,0x3a523af7,0x37e238c1,0x38a5398a,0x344f3624,0x3527374c,0x27c130d4,0x28aa31cc,0xb2bcadcf,0xb409aefb,0xb706b53c,0xb828b63e,0xb922b85b,0xb9f2b91b,0xba75b9d7,0xbb3cbaa9,
0x3a6a3b0d,0x3b113b9c,0x38bb39a2,0x39603a51,0x35423770,0x36153846,0x28c331eb,0x298c32e1,0xb41faf21,0xb4c8b026,0xb83cb65e,0xb8d7b757,0xba0ab932,0xbab8b9de,0xbb50bac0,0xbbcbbb5e,
0x3a813b22,0x3b243ba9,0x38d039b9,0x39743a65,0x355d3795,0x362f3857,0x28dc320a,0x29a53300,0xb434af46,0xb4ddb039,0xb850b67d,0xb8eab776,0xba22b949,0xbacbb9f2,0xbb63bad7,0xbbd6bb6e,
0x3a973b36,0x3b353bb6,0x38e539d0,0x39873a79,0x357737b8,0x36493868,0x28f53229,0x29be331e,0xb449af6c,0xb4f1b04b,0xb864b69d,0xb8fdb795,0xba39b95f,0xbadeba06,0xbb75baec,0xbbdfbb7d,
0x3aad3b4a,0x3b463bc2,0x38fa39e7,0x399a3a8c,0x359237dc,0x36633879,0x290e3247,0x29d7333d,0xb45eaf91,0xb506b05e,0xb878b6bc,0xb90fb7b3,0xba4fb975,0xbaf0ba19,0xbb86bb01,0xbbe7bb8c,
0x3ac33b5c,0x3b563bcc,0x390f39fd,0x39ad3a9f,0x35ac3800,0x367d388a,0x29273266,0x29f0335c,0xb473afb6,0xb51bb071,0xb88bb6dc,0xb921b7d1,0xba65b98a,0xbb02ba2d,0xbb96bb15,0xbbeebb99,
0x3ad73b6d,0x3b653bd6,0x39243a12,0x39c03ab1,0x35c73811,0x3697389b,0x29403285,0x2a09337a,0xb488afdc,0xb530b083,0xb89eb6fb,0xb933b7ef,0xba7ab9a0,0xbb13ba3f,0xbba5bb28,0xbbf4bba6,
0x3aeb3b7e,0x3b743bdf,0x39383a28,0x39d23ac3,0x35e13823,0x36b138ab,0x295932a4,0x2a223399,0xb49db001,0xb545b096,0xb8b2b71a,0xb945b807,0xba8fb9b5,0xbb24ba52,0xbbb3bb3b,0xbbf9bbb2,
0x3aff3b8d,0x3b823be6,0x394c3a3c,0x39e43ad4,0x35fb3834,0x36ca38bc,0x297232c2,0x2a3b33b7,0xb4b3b013,0xb55ab0a9,0xb8c5b739,0xb957b815,0xbaa4b9ca,0xbb34ba64,0xbbc0bb4d,0xbbfcbbbd,
0x39b839ba,0x3a973ab5,0x39b339b5,0x3a583a78,0x39af39b1,0x3a153a37,0x39aa39ad,0x39cd39f2,0x39a639a8,0x398239a8,0x39a139a4,0x3933395b,0x399d399f,0x38e03909,0x3999399b,0x388938b5,
0xb979b972,0xb865b832,0xb986b980,0xb8c7b896,0xb994b98d,0xb924b8f6,0xb9a1b99b,0xb97db951,0xb9afb9a8,0xb9d2b9a8,0xb9bcb9b5,0xba21b9fa,0xb9c9b9c3,0xba6bba47,0xb9d6b9d0,0xbab0ba8e,
0xb9f4b9fe,0xbac7bae9,0xb9dfb9e9,0xba7ebaa3,0xb9c9b9d4,0xba2dba56,0xb9b3b9be,0xb9d6ba02,0xb99db9a8,0xb979b9a8,0xb986b992,0xb916b948,0xb970b97b,0xb8adb8e2,0xb958b964,0xb840b877,
0x39373927,0x381a37b7,0x39583948,0x38943858,0x39793969,0x390738ce,0x39993989,0x3974393e,0x39b839a8,0x39da39a8,0x39d639c7,0x3a393a0b,0x39f439e5,0x3a903a65,0x3a113a02,0x3ade3ab8,
0x3a2d3a3f,0x3af43b1a,0x3a093a1b,0x3aa23acc,0x39e339f6,0x3a453a74,0x39bc39d0,0x39df3a13,0x399439a8,0x397039a8,0x396b3980,0x38f83935,0x39413956,0x387a38ba,0x3916392b,0x37e83838,
0xb8f3b8d8,0xb79bb705,0xb929b90e,0xb85fb817,0xb95db943,0xb8eab8a6,0xb990b976,0xb96bb92b,0xb9c0b9a8,0xb9e3b9a8,0xb9f0b9d8,0xba50ba1b,0xba1dba07,0xbab3ba83,0xba49ba33,0xbb0abae0,
0xba64ba7c,0xbb1ebb46,0xba31ba4b,0xbac4baf3,0xb9fcba17,0xba5cba92,0xb9c5b9e1,0xb9e7ba23,0xb98bb9a8,0xb966b9a8,0xb94fb96d,0xb8dbb922,0xb911b930,0xb845b891,0xb8d1b8f1,0xb74eb7ee,
0x38ad3887,0x36ff364e,0x38f838d3,0x382a37ac,0x3941391d,0x38cc387c,0x39863964,0x39623918,0x39c939a8,0x39eb39a8,0x3a0939e9,0x3a673a2b,0x3a453a27,0x3ad53aa0,0x3a7e3a62,0x3b323b05,
0x3b453b6e,0x3bbc3bdd,0x3ae53b17,0x3b573b8f,0x3a733aae,0x3ac73b14,0x39f03a33,0x3a113a71,0x395d39a8,0x393739a8,0x38bc390e,0x384038bf,0x380f3867,0x365f3775,0x36af376a,0x341a3540,
0xb65fb593,0xb389b115,0xb7e8b726,0xb625b4f9,0xb8adb852,0xb830b748,0xb958b905,0xb933b8b5,0xb9f4b9a8,0xba15b9a8,0xba7eba3b,0xbad1ba78,0xbaf4babc,0xbb63bb20,0xbb57bb28,0xbbc6bb9b,
0xbb68bb91,0xbbd0bbed,0xbb04bb39,0xbb6fbba6,0xba89bac9,0xbadbbb2b,0xb9f8ba43,0xba19ba7f,0xb954b9a8,0xb92eb9a8,0xb89eb8fb,0xb820b8ab,0xb7b2b83d,0xb5ebb71b,0xb60eb6e3,0xb2deb4b1,
0x35bc34d5,0x32322f0e,0x377a369e,0x35b13469,0x388e3828,0x380f36ee,0x394f38f1,0x392938a0,0x39fc39a8,0x3a1d39a8,0x3a933a4b,0x3ae53a87,0x3b133ad6,0x3b7a3b36,0x3b783b49,0x3bd93bb1,
0x3b873baf,0x3be13bf8,0x3b213b58,0x3b853bbb,0x3a9e3ae3,0x3aee3b41,0x3a003a52,0x3a213a8e,0x394a39a8,0x392439a8,0x387f38e7,0x37fe3896,0x37423812,0x357636c1,0x356a3659,0x31853420,
0xb517b414,0xb0d7abd9,0xb70ab614,0xb53ab3ae,0xb86fb7f9,0xb7ddb693,0xb946b8dd,0xb91fb88c,0xba04b9a8,0xba25b9a8,0xbaa9ba5a,0xbaf7ba95,0xbb2fbaf0,0xbb90bb4b,0xbb96bb67,0xbbe8bbc4,
0xbba3bbc9,0xbbefbbff,0xbb3dbb74,0xbb9abbcd,0xbab3bafc,0xbb01bb55,0xba09ba62,0xba29ba9c,0xb941b9a8,0xb91bb9a8,0xb85fb8d3,0xb7bdb881,0xb6d2b7cd,0xb4ffb665,0xb4c3b5ce,0xb029b31b,
0x346f32a1,0x2ef52248,0x36993587,0x34c33288,0x385037a1,0x379b3637,0x393c38c9,0x39163877,0x3a0d39a8,0x3a2d39a8,0x3abd3a69,0x3b0a3aa3,0x3b4a3b08,0x3ba33b5f,0x3bb03b82,0x3bf43bd5,
0x3bf83c00,0x3bf93bd4,0x3bac3bdc,0x3be43bfe,0x3b133b69,0x3b543bab,0x3a313aaa,0x3a503ae0,0x391139a8,0x38ea39a8,0x377a386d,0x366b3817,0x34873608,0x313b348d,0x2d9731f4,0xad65291b,
0xac3828b6,0x2ec33365,0xb44bb160,0xb0bea57f,0xb759b5da,0xb648b45d,0xb90cb862,0xb8e5b80d,0xba35b9a8,0xba54b9a8,0xbb1bbab1,0xbb5cbae6,0xbbb5bb72,0xbbe9bbb2,0xbbfcbbe3,0xbbf5bc00,
0xbbfebbfc,0xbbefbbbc,0xbbbdbbe9,0xbbeebc00,0xbb24bb7b,0xbb63bbb9,0xba39bab8,0xba58baed,0xb907b9a8,0xb8e0b9a8,0xb737b858,0xb625b802,0xb40eb5ab,0xb042b42c,0xa9b1b0cb,0x30109a48,
0x25e4ad7e,0xb0beb475,0x33a23036,0x2f8ba3db,0x3715357c,0x360233f7,0x3902384d,0x38db37ee,0x3a3d39a8,0x3a5c39a8,0x3b2c3abf,0x3b6a3af3,0x3bc53b84,0x3bf23bc0,0x3bff3bee,0x3be93c00,
0x3c003bf4,0x3be23ba0,0x3bcc3bf3,0x3bf53bff,0x3b353b8c,0x3b713bc6,0x3a413ac6,0x3a603af9,0x38fd39a8,0x38d639a8,0x36f43842,0x35df37d8,0x3328354c,0x2e913396,0x16482f40,0xb16ca852,
0x251b304e,0x32193534,0xb2adae14,0xad972aac,0xb6d2b51d,0xb5bcb334,0xb8f8b838,0xb8d1b7c2,0xba45b9a8,0xba64b9a8,0xbb3dbacc,0xbb78baff,0xbbd3bb95,0xbbf8bbcb,0xbc00bbf7,0xbbdabbfd,
0xbbfebbe6,0xbbd2bb80,0xbbd9bbfa,0xbbfbbbfb,0xbb45bb9d,0xbb7fbbd1,0xba49bad3,0xba67bb05,0xb8f3b9a8,0xb8ccb9a8,0xb6afb82d,0xb599b7ac,0xb232b4ed,0xac9cb2d2,0x294dace7,0x32c62c83,
0xac06b1db,0xb371b5f1,0x31b62b75,0x2b43adb0,0x368d34bd,0x3576326f,0x38ee3822,0x38c73796,0x3a4d39a8,0x3a6b39a8,0x3b4c3ad9,0x3b853b0b,0x3bdf3ba4,0x3bfd3bd6,0x3bfc3bfd,0x3bc83bf8,
0x3bbd3b5a,0x3b473a99,0x3bfe3bf4,0x3bf93bbe,0x3b8b3bdb,0x3bb83bf7,0x3a6f3b11,0x3a8c3b3e,0x38c139a8,0x389939a8,0x35523780,0x343236cc,0x294d320d,0xad332de2,0xb40eaedc,0xb6a4b408,
0x346336aa,0x36f438b0,0xa6ad3004,0x2e2d3451,0xb52fb1aa,0xb40ead1a,0xb8bcb76a,0xb894b6b5,0xba73b9a8,0xba90b9a8,0xbb92bb17,0xbbbdbb43,0xbbffbbe0,0xbbf6bbf9,0xbbb2bbf0,0xbb35bbb4,
0xbba5bb30,0xbb21ba5e,0xbc00bbeb,0xbbf3bbaa,0xbb98bbe4,0xbbc2bbfb,0xba76bb1d,0xba93bb49,0xb8b7b9a8,0xb88eb9a8,0xb50bb753,0xb3d3b69e,0xa17fb147,0x2f27ac51,0x34b73099,0x37423499,
0xb50bb75e,0xb790b900,0x9cb6b12e,0xb010b4e1,0x34e730e4,0x33892b11,0x38b2373d,0x38893687,0x3a7a39a8,0x3a9739a8,0x3b9e3b22,0x3bc63b4e,0x3c003be8,0x3bef3bfd,0x3b983be5,0x3b0d3b9e,
0x3b893b02,0x3af73a1f,0x3c003bdf,0x3beb3b93,0x3ba33bec,0x3bcb3bfe,0x3a7e3b28,0x3a9b3b53,0x38ad39a8,0x388439a8,0x34c33726,0x33403670,0xa51b3080,0xb08d297f,0xb55eb1c3,0xb7ddb529,
0x35b13807,0x3815394d,0x28843257,0x31093570,0xb49fb01d,0xb2f7a7da,0xb8a8b710,0xb87fb659,0xba81b9a8,0xba9eb9a8,0xbba9bb2e,0xbbcfbb58,0xbbffbbef,0xbbe6bbff,0xbb7abbd7,0xbae1bb86,
0xbb6abad0,0xbacbb9dc,0xbbfdbbd0,0xbbe1bb79,0xbbaebbf2,0xbbd3bc00,0xba85bb33,0xbaa2bb5d,0xb8a3b9a8,0xb87ab9a8,0xb47bb6f9,0xb2adb642,0x2a7aaf72,0x3185a4b6,0x360232ea,0x383a35b6,
0xb654b85d,0xb85fb996,0xac38b37d,0xb201b5fd,0x34572eaa,0x32631e48,0x389e36e3,0x3874362b,0x3a8939a8,0x3aa539a8,0x3bb33b39,0x3bd73b62,0x3bfc3bf5,0x3bdc3c00,0x3b593bc7,0x3ab33b6b,
0x39b739b9,0x3a883aa6,0x39b239b4,0x3a483a68,0x39ae39b0,0x3a033a26,0x39a939ab,0x39bb39e0,0x39a539a7,0x396e3995,0x39a039a3,0x391e3947,0x399c399e,0x38ca38f5,0x3997399a,0x3873389f,
0xb97cb975,0xb87eb84c,0xb98ab983,0xb8deb8ae,0xb997b991,0xb93bb90d,0xb9a5b99e,0xb993b967,0xb9b2b9ab,0xb9e6b9bd,0xb9bfb9b9,0xba34ba0e,0xb9ccb9c6,0xba7dba59,0xb9d9b9d3,0xbac0ba9f,
0xb9efb9f9,0xbab6bad9,0xb9d9b9e4,0xba6aba91,0xb9c4b9cf,0xba18ba42,0xb9aeb9b9,0xb9bfb9ec,0xb997b9a3,0xb961b991,0xb981b98c,0xb8fcb92f,0xb96ab975,0xb892b8c8,0xb953b95e,0xb824b85c,
0x3940392f,0x383937f6,0x39613950,0x38b13876,0x39813971,0x392338eb,0x39a03991,0x398e395a,0x39bf39b0,0x39f339c1,0x39de39cf,0x3a4f3a22,0x39fb39ec,0x3aa43a7b,0x3a183a0a,0x3af03acb,
0x3a243a36,0x3ae13b07,0x39ff3a12,0x3a8b3ab7,0x39d939ec,0x3a2c3a5d,0x39b239c6,0x39c439f9,0x398a399e,0x3953398c,0x39613975,0x38d93917,0x3936394b,0x3859389a,0x390b3921,0x37a43816,
0xb901b8e6,0xb7e6b750,0xb936b91c,0xb883b83c,0xb96ab950,0xb90bb8c8,0xb99cb983,0xb98ab94b,0xb9ccb9b4,0xb9ffb9c6,0xb9fbb9e4,0xba6aba36,0xba28ba12,0xbacaba9b,0xba53ba3e,0xbb1dbaf5,
0xba57ba70,0xbb09bb33,0xba24ba3e,0xbaabbadc,0xb9efba0a,0xba40ba77,0xb9b7b9d3,0xb9c8ba05,0xb97cb99a,0xb944b988,0xb940b95e,0xb8b6b8fe,0xb901b921,0xb81eb86b,0xb8c0b8e1,0xb6fcb79e,
0x38c0389a,0x375636a7,0x390b38e6,0x38543800,0x3953392f,0x38f238a4,0x39973975,0x3985393d,0x39d939b9,0x3a0c39ca,0x3a1839f9,0x3a843a4a,0x3a533a36,0x3aed3abb,0x3a8b3a70,0x3b473b1c,
0x3b2e3b5a,0x3ba63bce,0x3aca3afe,0x3b373b74,0x3a533a91,0x3a9d3aef,0x39cc3a12,0x39de3a42,0x39363983,0x38fc3971,0x389238e6,0x37fb3880,0x37c5383c,0x35d136eb,0x3651370d,0x330934ae,
0xb6c3b5fa,0xb460b251,0xb824b788,0xb6b8b590,0xb8d9b880,0xb873b7d5,0xb981b92f,0xb96eb8f5,0xba18b9cf,0xba48b9e0,0xba9dba5d,0xbafabaa6,0xbb0fbad9,0xbb80bb43,0xbb6cbb40,0xbbd8bbb2,
0xbb51bb7d,0xbbbdbbe0,0xbae7bb1f,0xbb4ebb8c,0xba66baa9,0xbaafbb04,0xb9d1ba1e,0xb9e2ba4e,0xb928b97e,0xb8edb96c,0xb86eb8cd,0xb7afb866,0xb74bb80b,0xb54fb684,0xb5a2b679,0xb197b411,
0x362e3549,0x338330de,0x37e6370d,0x3651350e,0x38c0385c,0x38593788,0x397c3921,0x396a38e6,0x3a2439d3,0x3a5339e4,0x3ab63a70,0x3b0f3ab7,0x3b2e3af5,0x3b973b5a,0x3b8d3b61,0x3be83bc7,
0x3b703b9c,0x3bd03bef,0x3b033b3d,0x3b653ba2,0x3a793ac1,0x3ac03b19,0x39d53a2a,0x39e63a59,0x3919397a,0x38de3967,0x384938b4,0x3761384c,0x36cf37b4,0x34cc361d,0x34f035e2,0x302332e4,
0xb596b496,0xb244aecf,0xb783b690,0xb5e8b48a,0xb8a7b836,0xb83eb73a,0xb978b912,0xb965b8d7,0xba30b9d7,0xba5fb9e8,0xbacdba82,0xbb23bac8,0xbb4cbb10,0xbbacbb6f,0xbbaabb7f,0xbbf4bbd8,
0xbb8dbbb7,0xbbe0bbf9,0xbb1dbb5a,0xbb7abbb5,0xba8bbad9,0xbad0bb2d,0xb9d9ba36,0xb9eaba65,0xb90bb975,0xb8cfb963,0xb824b89a,0xb713b831,0xb651b750,0xb447b5b3,0xb43bb549,0xad58b1a4,
0x34fc33c0,0x31032bc0,0x371e3611,0x357e3405,0x388d3811,0x382436eb,0x39733903,0x396138c8,0x3a3c39db,0x3a6a39ec,0x3ae43a94,0x3b373ad9,0x3b673b2a,0x3bbe3b83,0x3bc33b9a,0x3bfc3be7,
0x3bed3bff,0x3bff3bea,0x3b8d3bc7,0x3bcc3bf5,0x3ae13b40,0x3b1d3b83,0x39ef3a70,0x39ff3a9b,0x38c0395e,0x3883394b,0x36c33816,0x357e3750,0x33833549,0x2e84332e,0x28cf3061,0xb0aca5b2,
0xaf7ea376,0x29663166,0xb514b2fd,0xb2bfad71,0xb809b69b,0xb734b555,0xb95cb8b9,0xb949b87b,0xba75b9f1,0xbaa1ba01,0xbb49bae9,0xbb8bbb25,0xbbcfbb96,0xbbf9bbd2,0xbc00bbf2,0xbbe3bbfe,
0xbbf6bc00,0xbbfcbbda,0xbb9fbbd6,0xbbd8bbfb,0xbaf0bb52,0xbb2cbb92,0xb9f3ba7b,0xba03baa6,0xb8b1b95a,0xb873b947,0xb673b7f6,0xb52cb718,0xb276b4de,0xac5eb251,0x2052ae39,0x321f2bf2,
0x2cf4a806,0xad3fb2d8,0x34a831ee,0x31e22a93,0x37db364b,0x36fc3502,0x395738a9,0x3944386b,0x3a8039f5,0x3aab3a05,0x3b5b3af8,0x3b993b33,0x3bdd3ba7,0x3bfd3bdd,0x3bff3bfa,0x3bd13bf9,
0x3bfd3bfd,0x3bf53bc6,0x3baf3be3,0x3be23bff,0x3b003b64,0x3b393ba0,0x39f73a86,0x3a083ab0,0x38a23955,0x38633942,0x362237bf,0x34d836e0,0x31663472,0x286b3172,0xaaf82b5c,0xb390ae84,
0xa8cf2cf4,0x2fc93423,0xb43bb0de,0xb103a484,0xb7a4b5fa,0xb6c3b4ae,0xb953b89a,0xb940b85c,0xba8bb9f9,0xbab6ba0a,0xbb6cbb07,0xbba6bb40,0xbbe8bbb7,0xbc00bbe7,0xbbfabbff,0xbbbabbf1,
0xbc00bbf6,0xbbebbbae,0xbbbebbed,0xbbebbc00,0xbb0fbb74,0xbb47bbad,0xb9fbba91,0xba0cbabb,0xb892b950,0xb854b93d,0xb5d1b788,0xb484b6a7,0xb055b405,0x9248b093,0x2e6ba484,0x347e3086,
0x98b6afe2,0xb128b4d8,0x339c2f97,0x3023a420,0x376c35a8,0x368a345a,0x394e388b,0x393b384c,0x3a9639fd,0x3ac03a0e,0x3b7c3b16,0x3bb33b4d,0x3bf23bc5,0x3c003bef,0x3bf03c00,0x3ba03be5,
0x3bde3b91,0x3b8a3af7,0x3bf23bff,0x3c003be3,0x3b533bb9,0x3b823bdf,0x3a103ac5,0x3a203aec,0x38443939,0x38033925,0x342f366d,0x31b03584,0xa8392f65,0xb15a1d7f,0xb531b1c9,0xb7e0b55b,
0x3269358a,0x35a83819,0xae842a61,0x205231e2,0xb651b405,0xb567b15a,0xb936b83c,0xb923b7f6,0xbacaba12,0xbaf0ba22,0xbbbebb5a,0xbbe3bb88,0xbbfdbbf5,0xbbddbc00,0xbb81bbd6,0xbadfbb7c,
0xbbcebb70,0xbb6dbac6,0xbbf8bbfb,0xbbffbbd6,0xbb60bbc4,0xbb8dbbe7,0xba14bacf,0xba24baf5,0xb834b934,0xb7e6b921,0xb3b4b634,0xb103b549,0x2c44ada3,0x326925b2,0x35e23309,0x384135f4,
0xb3a8b63a,0xb63fb869,0x2cc2ad58,0xa89db2f0,0x3617335f,0x352c30ac,0x3931382c,0x391e37d5,0x3ad43a16,0x3afa3a26,0x3bc93b66,0x3bea3b92,0x3bf93bfa,0x3bcf3bff,0x3b5f3bc5,0x3aad3b5d,
0x3bba3b4c,0x3b4d3a93,0x3bfc3bf6,0x3bfd3bc7,0x3b6c3bce,0x3b973bed,0x3a183ad9,0x3a283afe,0x3824392f,0x37c5391c,0x330935fa,0x3055350e,0xae6b2bc0,0xb377aa61,0xb690b423,0xb890b68a,
0x347236e5,0x36d438b6,0xa9fd2f7e,0x2c1233fd,0xb5dcb2b3,0xb4f0affb,0xb92db81c,0xb919b7b4,0xbaddba1a,0xbb03ba2a,0xbbd3bb72,0xbbf0bb9c,0xbbf2bbfe,0xbbbfbbfc,0xbb38bbaf,0xba77bb3c,
0xbba4bb23,0xbb2aba5b,0xbbffbbee,0xbbfabbb6,0xbb77bbd7,0xbba1bbf3,0xba1cbae2,0xba2cbb07,0xb813b92a,0xb7a4b917,0xb25db5bf,0xaf4cb4d2,0x3048a839,0x34412cf4,0x373a34c0,0x38dc371e,
0xb50eb78e,0xb767b901,0x24e9b0d1,0xadd5b484,0x35a23207,0x34b42e9d,0x3928380b,0x39143793,0x3ae73a1e,0x3b0c3a2e,0x3bdb3b7d,0x3bf53ba6,0x3be93c00,0x3bad3bf7,0x3b0d3b97,0x3a3e3b18,
0xb999b996,0xb889b85d,0xb99db99b,0xb8e0b8b5,0xb9a1b99f,0xb933b909,0xb9a6b9a4,0xb982b95b,0xb9aab9a8,0xb9cdb9a8,0xb9afb9ad,0xba15b9f2,0xb9b3b9b1,0xba58ba37,0xb9b8b9b5,0xba97ba78,
0xb9d6b9dc,0xbab0bad0,0xb9c9b9d0,0xba6bba8e,0xb9bcb9c3,0xba21ba47,0xb9afb9b5,0xb9d2b9fa,0xb9a1b9a8,0xb97db9a8,0xb994b99b,0xb924b951,0xb986b98d,0xb8c7b8f6,0xb979b980,0xb865b896,
0x3958394d,0x38403807,0x39703964,0x38ad3877,0x3986397b,0x391638e2,0x399d3992,0x39793948,0x39b339a8,0x39d639a8,0x39c939be,0x3a2d3a02,0x39df39d4,0x3a7e3a56,0x39f439e9,0x3ac73aa3,
0x3a113a1f,0x3ade3b02,0x39f43a02,0x3a903ab8,0x39d639e5,0x3a393a65,0x39b839c7,0x39da3a0b,0x399939a8,0x397439a8,0x39793989,0x3907393e,0x39583969,0x389438ce,0x39373948,0x381a3858,
0xb916b900,0xb7e8b75e,0xb941b92b,0xb87ab838,0xb96bb956,0xb8f8b8ba,0xb994b980,0xb970b935,0xb9bcb9a8,0xb9dfb9a8,0xb9e3b9d0,0xba45ba13,0xba09b9f6,0xbaa2ba74,0xba2dba1b,0xbaf4bacc,
0xba49ba5e,0xbb0abb30,0xba1dba33,0xbab3bae0,0xb9f0ba07,0xba50ba83,0xb9c0b9d8,0xb9e3ba1b,0xb990b9a8,0xb96bb9a8,0xb95db976,0xb8eab92b,0xb929b943,0xb85fb8a6,0xb8f3b90e,0xb79bb817,
0x38d138b0,0x374e36aa,0x391138f1,0x384537ee,0x394f3930,0x38db3891,0x398b396d,0x39663922,0x39c539a8,0x39e739a8,0x39fc39e1,0x3a5c3a23,0x3a313a17,0x3ac43a92,0x3a643a4b,0x3b1e3af3,
0x3a7e3a99,0x3b323b5a,0x3a453a62,0x3ad53b05,0x3a093a27,0x3a673aa0,0x39c939e9,0x39eb3a2b,0x398639a8,0x396239a8,0x39413964,0x38cc3918,0x38f8391d,0x382a387c,0x38ad38d3,0x36ff37ac,
0xb6afb5f1,0xb41ab1db,0xb80fb76a,0xb65fb540,0xb8bcb867,0xb840b775,0xb95db90e,0xb937b8bf,0xb9f0b9a8,0xba11b9a8,0xba73ba33,0xbac7ba71,0xbae5baae,0xbb57bb14,0xbb45bb17,0xbbbcbb8f,
0xbb57bb80,0xbbc6bbe6,0xbaf4bb28,0xbb63bb9b,0xba7ebabc,0xbad1bb20,0xb9f4ba3b,0xba15ba78,0xb958b9a8,0xb933b9a8,0xb8adb905,0xb830b8b5,0xb7e8b852,0xb625b748,0xb65fb726,0xb389b4f9,
0x360e3534,0x32de304e,0x37b236e3,0x35eb34b1,0x389e383d,0x3820371b,0x395438fb,0x392e38ab,0x39f839a8,0x3a1939a8,0x3a893a43,0x3adb3a7f,0x3b043ac9,0x3b6f3b2b,0x3b683b39,0x3bd03ba6,
0x3b783ba0,0x3bd93bf4,0x3b133b49,0x3b7a3bb1,0x3a933ad6,0x3ae53b36,0x39fc3a4b,0x3a1d3a87,0x394f39a8,0x392939a8,0x388e38f1,0x380f38a0,0x377a3828,0x35b136ee,0x35bc369e,0x32323469,
0xb56ab475,0xb185ad7e,0xb742b659,0xb576b420,0xb87fb812,0xb7feb6c1,0xb94ab8e7,0xb924b896,0xba00b9a8,0xba21b9a8,0xba9eba52,0xbaeeba8e,0xbb21bae3,0xbb85bb41,0xbb87bb58,0xbbe1bbbb,
0xbb96bbbc,0xbbe8bbfc,0xbb2fbb67,0xbb90bbc4,0xbaa9baf0,0xbaf7bb4b,0xba04ba5a,0xba25ba95,0xb946b9a8,0xb91fb9a8,0xb86fb8dd,0xb7ddb88c,0xb70ab7f9,0xb53ab693,0xb517b614,0xb0d7b3ae,
0x34c33365,0x302928b6,0x36d235ce,0x34ff331b,0x385f37cd,0x37bd3665,0x394138d3,0x391b3881,0x3a0939a8,0x3a2939a8,0x3ab33a62,0x3b013a9c,0x3b3d3afc,0x3b9a3b55,0x3ba33b74,0x3bef3bcd,
0x3bb03bd4,0x3bf43c00,0x3b4a3b82,0x3ba33bd5,0x3abd3b08,0x3b0a3b5f,0x3a0d3a69,0x3a2d3aa3,0x393c39a8,0x391639a8,0x385038c9,0x379b3877,0x369937a1,0x34c33637,0x346f3587,0x2ef53288,
0xad972248,0x2d6532a1,0xb487b1f4,0xb13ba91b,0xb77ab608,0xb66bb48d,0xb911b86d,0xb8eab817,0xba31b9a8,0xba50b9a8,0xbb13baaa,0xbb54bae0,0xbbacbb69,0xbbe4bbab,0xbbf8bbdc,0xbbf9bbfe,
0xbbfcbbff,0xbbf5bbc9,0xbbb5bbe3,0xbbe9bc00,0xbb1bbb72,0xbb5cbbb2,0xba35bab1,0xba54bae6,0xb90cb9a8,0xb8e5b9a8,0xb759b862,0xb648b80d,0xb44bb5da,0xb0beb45d,0xac38b160,0x2ec3a57f,
0x29b1abd9,0xb010b414,0x340e30cb,0x30421a48,0x373735ab,0x3625342c,0x39073858,0x38e03802,0x3a3939a8,0x3a5839a8,0x3b243ab8,0x3b633aed,0x3bbd3b7b,0x3bee3bb9,0x3bfe3be9,0x3bef3c00,
0x3bff3bf8,0x3be93baf,0x3bc53bee,0x3bf23c00,0x3b2c3b84,0x3b6a3bc0,0x3a3d3abf,0x3a5c3af3,0x390239a8,0x38db39a8,0x3715384d,0x360237ee,0x33a2357c,0x2f8b33f7,0x25e43036,0xb0bea3db,
0x96482f0e,0x316c34d5,0xb328af40,0xae912852,0xb6f4b54c,0xb5dfb396,0xb8fdb842,0xb8d6b7d8,0xba41b9a8,0xba60b9a8,0xbb35bac6,0xbb71baf9,0xbbccbb8c,0xbbf5bbc6,0xbc00bbf3,0xbbe2bbff,
0xbc00bbed,0xbbdabb91,0xbbd3bbf7,0xbbf8bbfd,0xbb3dbb95,0xbb78bbcb,0xba45bacc,0xba64baff,0xb8f8b9a8,0xb8d1b9a8,0xb6d2b838,0xb5bcb7c2,0xb2adb51d,0xad97b334,0x251bae14,0x32192aac,
0xa94db115,0xb2c6b593,0x32322ce7,0x2c9cac83,0x36af34ed,0x359932d2,0x38f3382d,0x38cc37ac,0x3a4939a8,0x3a6739a8,0x3b453ad3,0x3b7f3b05,0x3bd93b9d,0x3bfb3bd1,0x3bfe3bfa,0x3bd23bfb,
0x3bfc3bdd,0x3bc83b6e,0x3bdf3bfd,0x3bfd3bf8,0x3b4c3ba4,0x3b853bd6,0x3a4d3ad9,0x3a6b3b0b,0x38ee39a8,0x38c739a8,0x368d3822,0x35763796,0x31b634bd,0x2b43326f,0xac062b75,0xb371adb0,
0x340e364e,0x36a43887,0xa94d2edc,0x2d333408,0xb552b20d,0xb432ade2,0xb8c1b780,0xb899b6cc,0xba6fb9a8,0xba8cb9a8,0xbb8bbb11,0xbbb8bb3e,0xbbfebbdb,0xbbf9bbf7,0xbbbdbbf4,0xbb47bbbe,
0xbbb2bb46,0xbb35ba7c,0xbbffbbf0,0xbbf6bbb4,0xbb92bbe0,0xbbbdbbf9,0xba73bb17,0xba90bb43,0xb8bcb9a8,0xb894b9a8,0xb52fb76a,0xb40eb6b5,0xa6adb1aa,0x2e2dad1a,0x34633004,0x36f43451,
0xb4b7b705,0xb742b8d8,0x217fb099,0xaf27b499,0x350b3147,0x33d32c51,0x38b73753,0x388e369e,0x3a7639a8,0x3a9339a8,0x3b983b1d,0x3bc23b49,0x3c003be4,0x3bf33bfb,0x3ba53beb,0x3b213baa,
0x3b983b1a,0x3b0d3a3f,0x3c003be5,0x3bef3b9e,0x3b9e3be8,0x3bc63bfd,0x3a7a3b22,0x3a973b4e,0x38b239a8,0x388939a8,0x34e7373d,0x33893687,0x9cb630e4,0xb0102b11,0xb50bb12e,0xb790b4e1,
0x355e37b7,0x37dd3927,0x251b31c3,0x308d3529,0xb4c3b080,0xb340a97f,0xb8adb726,0xb884b670,0xba7eb9a8,0xba9bb9a8,0xbba3bb28,0xbbcbbb53,0xbc00bbec,0xbbebbbfe,0xbb89bbdf,0xbaf7bb93,
0xbb7abae9,0xbae1b9fe,0xbbffbbd7,0xbbe6bb86,0xbba9bbef,0xbbcfbbff,0xba81bb2e,0xba9ebb58,0xb8a8b9a8,0xb87fb9a8,0xb49fb710,0xb2f7b659,0x2884b01d,0x3109a7da,0x35b13257,0x38153570,
0xb602b832,0xb83ab972,0xaa7ab2ea,0xb185b5b6,0x347b2f72,0x32ad24b6,0x38a336f9,0x387a3642,0x3a8539a8,0x3aa239a8,0x3bae3b33,0x3bd33b5d,0x3bfd3bf2,0x3be13c00,0x3b6a3bd0,0x3acb3b79,
0x3b593ab5,0x3ab339ba,0x3bfc3bc7,0x3bdc3b6b,0x3bb33bf5,0x3bd73c00,0x3a893b39,0x3aa53b62,0x389e39a8,0x387439a8,0x345736e3,0x3263362b,0xac382eaa,0xb2011e48,0xb654b37d,0xb85fb5fd,
0xb99ab997,0xb89fb873,0xb99eb99c,0xb8f5b8ca,0xb9a3b9a0,0xb947b91e,0xb9a7b9a5,0xb995b96e,0xb9abb9a9,0xb9e0b9bb,0xb9b0b9ae,0xba26ba03,0xb9b4b9b2,0xba68ba48,0xb9b9b9b7,0xbaa6ba88,
0xb9d3b9d9,0xba9fbac0,0xb9c6b9cc,0xba59ba7d,0xb9b9b9bf,0xba0eba34,0xb9abb9b2,0xb9bdb9e6,0xb99eb9a5,0xb967b993,0xb991b997,0xb90db93b,0xb983b98a,0xb8aeb8de,0xb975b97c,0xb84cb87e,
0x395e3953,0x385c3824,0x3975396a,0x38c83892,0x398c3981,0x392f38fc,0x39a33997,0x39913961,0x39b939ae,0x39ec39bf,0x39cf39c4,0x3a423a18,0x39e439d9,0x3a913a6a,0x39f939ef,0x3ad93ab6,
0x3a0a3a18,0x3acb3af0,0x39ec39fb,0x3a7b3aa4,0x39cf39de,0x3a223a4f,0x39b039bf,0x39c139f3,0x399139a0,0x395a398e,0x39713981,0x38eb3923,0x39503961,0x387638b1,0x392f3940,0x37f63839,
0xb921b90b,0xb816b7a4,0xb94bb936,0xb89ab859,0xb975b961,0xb917b8d9,0xb99eb98a,0xb98cb953,0xb9c6b9b2,0xb9f9b9c4,0xb9ecb9d9,0xba5dba2c,0xba12b9ff,0xbab7ba8b,0xba36ba24,0xbb07bae1,
0xba3eba53,0xbaf5bb1d,0xba12ba28,0xba9bbaca,0xb9e4b9fb,0xba36ba6a,0xb9b4b9cc,0xb9c6b9ff,0xb983b99c,0xb94bb98a,0xb950b96a,0xb8c8b90b,0xb91cb936,0xb83cb883,0xb8e6b901,0xb750b7e6,
0x38e138c0,0x379e36fc,0x39213901,0x386b381e,0x395e3940,0x38fe38b6,0x399a397c,0x39883944,0x39d339b7,0x3a0539c8,0x3a0a39ef,0x3a773a40,0x3a3e3a24,0x3adc3aab,0x3a703a57,0x3b333b09,
0x3a703a8b,0x3b1c3b47,0x3a363a53,0x3abb3aed,0x39f93a18,0x3a4a3a84,0x39b939d9,0x39ca3a0c,0x39753997,0x393d3985,0x392f3953,0x38a438f2,0x38e6390b,0x38003854,0x389a38c0,0x36a73756,
0xb70db651,0xb4aeb309,0xb83cb7c5,0xb6ebb5d1,0xb8e6b892,0xb880b7fb,0xb983b936,0xb971b8fc,0xba12b9cc,0xba42b9de,0xba91ba53,0xbaefba9d,0xbafebaca,0xbb74bb37,0xbb5abb2e,0xbbcebba6,
0xbb40bb6c,0xbbb2bbd8,0xbad9bb0f,0xbb43bb80,0xba5dba9d,0xbaa6bafa,0xb9cfba18,0xb9e0ba48,0xb92fb981,0xb8f5b96e,0xb880b8d9,0xb7d5b873,0xb788b824,0xb590b6b8,0xb5fab6c3,0xb251b460,
0x367935a2,0x34113197,0x380b374b,0x3684354f,0x38cd386e,0x386637af,0x397e3928,0x396c38ed,0x3a1e39d1,0x3a4e39e2,0x3aa93a66,0x3b043aaf,0x3b1f3ae7,0x3b8c3b4e,0x3b7d3b51,0x3be03bbd,
0x3b613b8d,0x3bc73be8,0x3af53b2e,0x3b5a3b97,0x3a703ab6,0x3ab73b0f,0x39d33a24,0x39e43a53,0x3921397c,0x38e6396a,0x385c38c0,0x37883859,0x370d37e6,0x350e3651,0x3549362e,0x30de3383,
0xb5e2b4f0,0xb2e4b023,0xb7b4b6cf,0xb61db4cc,0xb8b4b849,0xb84cb761,0xb97ab919,0xb967b8de,0xba2ab9d5,0xba59b9e6,0xbac1ba79,0xbb19bac0,0xbb3dbb03,0xbba2bb65,0xbb9cbb70,0xbbefbbd0,
0xbb7fbbaa,0xbbd8bbf4,0xbb10bb4c,0xbb6fbbac,0xba82bacd,0xbac8bb23,0xb9d7ba30,0xb9e8ba5f,0xb912b978,0xb8d7b965,0xb836b8a7,0xb73ab83e,0xb690b783,0xb48ab5e8,0xb496b596,0xaecfb244,
0x3549343b,0x31a42d58,0x37503651,0x35b33447,0x389a3824,0x38313713,0x3975390b,0x396338cf,0x3a3639d9,0x3a6539ea,0x3ad93a8b,0x3b2d3ad0,0x3b5a3b1d,0x3bb53b7a,0x3bb73b8d,0x3bf93be0,
0x3b9a3bc3,0x3be73bfc,0x3b2a3b67,0x3b833bbe,0x3a943ae4,0x3ad93b37,0x39db3a3c,0x39ec3a6a,0x39033973,0x38c83961,0x3811388d,0x36eb3824,0x3611371e,0x3405357e,0x33c034fc,0x2bc03103,
0xb061a8cf,0x25b230ac,0xb549b383,0xb32eae84,0xb816b6c3,0xb750b57e,0xb95eb8c0,0xb94bb883,0xba70b9ef,0xba9bb9ff,0xbb40bae1,0xbb83bb1d,0xbbc7bb8d,0xbbf5bbcc,0xbbffbbed,0xbbeabbff,
0xbbf2bc00,0xbbfebbe3,0xbb96bbcf,0xbbd2bbf9,0xbae9bb49,0xbb25bb8b,0xb9f1ba75,0xba01baa1,0xb8b9b95c,0xb87bb949,0xb69bb809,0xb555b734,0xb2fdb514,0xad71b2bf,0xa376af7e,0x31662966,
0x2e39a052,0xabf2b21f,0x34de3276,0x32512c5e,0x37f63673,0x3718352c,0x395a38b1,0x39473873,0x3a7b39f3,0x3aa63a03,0x3b523af0,0x3b923b2c,0x3bd63b9f,0x3bfb3bd8,0x3c003bf6,0x3bda3bfc,
0x3bfa3bff,0x3bf93bd1,0x3ba73bdd,0x3bdd3bfd,0x3af83b5b,0x3b333b99,0x39f53a80,0x3a053aab,0x38a93957,0x386b3944,0x364b37db,0x350236fc,0x31ee34a8,0x2a9331e2,0xa8062cf4,0xb2d8ad3f,
0xab5c2af8,0x2e843390,0xb472b166,0xb172a86b,0xb7bfb622,0xb6e0b4d8,0xb955b8a2,0xb942b863,0xba86b9f7,0xbab0ba08,0xbb64bb00,0xbba0bb39,0xbbe3bbaf,0xbbffbbe2,0xbbfdbbfd,0xbbc6bbf5,
0xbbffbbfa,0xbbf1bbba,0xbbb7bbe8,0xbbe7bc00,0xbb07bb6c,0xbb40bba6,0xb9f9ba8b,0xba0abab6,0xb89ab953,0xb85cb940,0xb5fab7a4,0xb4aeb6c3,0xb0deb43b,0xa484b103,0x2cf4a8cf,0x34232fc9,
0x2484ae6b,0xb086b47e,0x34053055,0x30931248,0x378835d1,0x36a73484,0x39503892,0x393d3854,0x3a9139fb,0x3abb3a0c,0x3b743b0f,0x3bad3b47,0x3bed3bbe,0x3c003beb,0x3bf63c00,0x3bae3beb,
0x3c003bf0,0x3be53ba0,0x3bc53bf2,0x3bef3c00,0x3b163b7c,0x3b4d3bb3,0x39fd3a96,0x3a0e3ac0,0x388b394e,0x384c393b,0x35a8376c,0x345a368a,0x2f97339c,0xa4203023,0xafe298b6,0xb4d8b128,
0x31c93531,0x355b37e0,0xaf652839,0x9d7f315a,0xb66db42f,0xb584b1b0,0xb939b844,0xb925b803,0xbac5ba10,0xbaecba20,0xbbb9bb53,0xbbdfbb82,0xbbffbbf2,0xbbe3bc00,0xbb91bbde,0xbaf7bb8a,
0xbbd6bb81,0xbb7cbadf,0xbbf5bbfd,0xbc00bbdd,0xbb5abbbe,0xbb88bbe3,0xba12baca,0xba22baf0,0xb83cb936,0xb7f6b923,0xb405b651,0xb15ab567,0x2a61ae84,0x31e22052,0x358a3269,0x381935a8,
0xb309b5e2,0xb5f4b841,0x2da3ac44,0xa5b2b269,0x363433b4,0x35493103,0x39343834,0x392137e6,0x3acf3a14,0x3af53a24,0x3bc43b60,0x3be73b8d,0x3bfb3bf8,0x3bd63bff,0x3b703bce,0x3ac63b6d,
0x3bc53b5f,0x3b5d3aad,0x3bfa3bf9,0x3bff3bcf,0x3b663bc9,0x3b923bea,0x3a163ad4,0x3a263afa,0x382c3931,0x37d5391e,0x335f3617,0x30ac352c,0xad582cc2,0xb2f0a89d,0xb63ab3a8,0xb869b63f,
0x34233690,0x368a3890,0xabc02e6b,0x2a613377,0xb5fab309,0xb50eb055,0xb92fb824,0xb91cb7c5,0xbad9ba18,0xbafeba28,0xbbcebb6c,0xbbedbb97,0xbbf6bbfc,0xbbc7bbfd,0xbb4cbbba,0xba93bb4d,
0xbbafbb38,0xbb3cba77,0xbbfebbf2,0xbbfcbbbf,0xbb72bbd3,0xbb9cbbf0,0xba1abadd,0xba2abb03,0xb81cb92d,0xb7b4b919,0xb2b3b5dc,0xaffbb4f0,0x2f7ea9fd,0x33fd2c12,0x36e53472,0x38b636d4,
0xb4c0b73a,0xb71eb8dc,0x2839b048,0xacf4b441,0x35bf325d,0x34d22f4c,0x392a3813,0x391737a4,0x3ae23a1c,0x3b073a2c,0x3bd73b77,0x3bf33ba1,0x3bee3bff,0x3bb63bfa,0x3b233ba4,0x3a5b3b2a,
0x3b973b0d,0x3b183a3e,0x3c003be9,0x3bf73bad,0x3b7d3bdb,0x3ba63bf5,0x3a1e3ae7,0x3a2e3b0c,0x380b3928,0x37933914,0x320735a2,0x2e9d34b4,0xb0d124e9,0xb484add5,0xb78eb50e,0xb901b767,
0xb97239ba,0x39dc3996,0xb8323ab5,0x3ad0385d,0x3927b9fe,0xba1fb94d,0x37b7bae9,0xbb02b807,0xb8d83a3f,0x3a5e3900,0xb7053b1a,0x3b30375e,0x3887ba7c,0xba99b8b0,0x364ebb46,0xbb5ab6aa,
0xb90039dc,0x3a3f3972,0xad7e3be6,0x3bf83115,0x3807ba99,0xbae9b887,0xabd9bc00,0xbbfca248,0xb5f13b30,0x3b6e3705,0x32a13bed,0x3bd4b04e,0x3365bba0,0xbbc9b4d5,0xb593bbaf,0xbb803475,
0xb88739fe,0x3a99394d,0x35f13bbc,0x3b6eb414,0x3593bb1a,0xbb80b75e,0xb8b0bb02,0xba7c37b7,0xaf0e3bc9,0x3bf43365,0x3a1f39dc,0x3927b972,0xb04ebc00,0xbbed2248,0xbb30b85d,0xb7053ab5,
0xb8073a1f,0x3ae93927,0x39fe3a3f,0x394db900,0x31dbbb80,0xbbddb593,0xbb6eb832,0xb5f13ad0,0x31153c00,0x3be62248,0x3bff32a1,0x28b6bbd4,0xb7b7bb91,0xbb023534,0xbba0304e,0x34d53bed,
0xb7053a3f,0x3b303900,0x3bbc375e,0x3414bb1a,0x2248bbc9,0xbc00b365,0xbbdda8b6,0x31db3bff,0x36aa3bd4,0x3b46b2a1,0x3a7cb64e,0xb8b0bb5a,0xba1fba5e,0xb92738d8,0xb7b739fe,0x3b02394d,
0xb5f13a5e,0x3b6e38d8,0x3bd42bd9,0xb2a1bbfc,0xb115bbf4,0xbbe6af0e,0xb9dc375e,0x39723b1a,0x39273b46,0x3a1fb6aa,0x3475bad0,0xbbafb832,0xbb91b887,0xb5343a99,0x34143c00,0x3bbc2248,
0xb4d53a7c,0x3ba038b0,0x3a3fb593,0xb900bb80,0xb534bc00,0xbb912248,0xb4143ab5,0x3bbc385d,0x3a993a5e,0x3887b8d8,0xb5f1bbfc,0xbb6e2bd9,0xbbffb475,0x28b63baf,0x3ad03a1f,0x3832b927,
0xb3653a99,0x3bc93887,0x36aab996,0xbb46b9ba,0xb7b7bbed,0xbb02304e,0x34d53bfc,0x3ba02bd9,0x3b913927,0x3534ba1f,0xbae9ba3f,0xb8073900,0xbb5a28b6,0x364e3bff,0x3bd43115,0xb2a1bbe6,
0xb1153ab5,0x3be6385d,0xa8b6bb6e,0xbbffb5f1,0xb900bbbc,0xba3f3414,0x3a1f3b30,0x3927b705,0x3bfc375e,0x2bd9bb1a,0xbbedb475,0x304e3baf,0xb9ba3593,0x39963b80,0x3887b832,0xba99bad0,
0xad7e3ad0,0x3bf83832,0xb7b7bbff,0xbb0228b6,0xb9febb6e,0xb94d35f1,0x3bed3887,0x304eba99,0x3bd43414,0xb2a1bbbc,0xb9963534,0x39ba3b91,0xb6aa3900,0x3b463a3f,0xb115bba0,0xbbe6b4d5,
0xa2483ae9,0x3c003807,0xba99bb30,0xb8873705,0xbad0bb02,0xb83237b7,0x3b462d7e,0xb6aabbf8,0x3b1a28b6,0xb75ebbff,0xaf0e3a7c,0x3bf438b0,0xabd93ab5,0x3bfc385d,0xba5ebb5a,0xb8d8364e,
0x2bd93b02,0x3bfc37b7,0xbbedb927,0xb04e3a1f,0xbb6eba7c,0xb5f138b0,0x385db6aa,0xbab5bb46,0x39dcb1db,0xb972bbdd,0x38323c00,0x3ad02248,0x34d53bbc,0x3ba03414,0xbbf4b705,0x2f0e3b30,
0x304e3b1a,0x3bed375e,0xbb91b475,0x35343baf,0xbbd4b9dc,0xb2a13972,0x2248ba7c,0xbc00b8b0,0x3832b64e,0xbad0bb5a,0x3b803a99,0x3593b887,0x39003bfc,0x3a3fabd9,0xb9273414,0x3a1f3bbc,
0x32a13b30,0x3bd43705,0xb996304e,0x39ba3bed,0xbbffb927,0xa8b63a1f,0xb832bbf4,0xbad0af0e,0x3475b8b0,0xbbafba7c,0x3ba03593,0xb4d5bb80,0x3ae93b6e,0x3807b5f1,0x2bd93a99,0x3bfc3887,
0x34753b46,0x3baf36aa,0xb4d53832,0x3ba03ad0,0xbbedb85d,0x304e3ab5,0xbb30bb5a,0xb705364e,0x2248b9fe,0xbc00b94d,0x3887b414,0xba99bbbc,0x3be63a1f,0x3115b927,0x39dc3bf4,0x3972af0e,
0x35933b5a,0x3b80364e,0x31153a99,0x3be63887,0xbba0b705,0x34d53b30,0xbbf4b8d8,0x2f0e3a5e,0xb414bb02,0xbbbcb7b7,0xabd9ba1f,0xbbfcb927,0x3bd43832,0xb2a1bad0,0x3c003972,0xa248b9dc,
0x36aa3b6e,0x3b4635f1,0x38b03bdd,0x3a7c31db,0xbb1ab534,0x375e3b91,0xba3fb04e,0x39003bed,0xb807bbaf,0xbae9b475,0xb94dbbf8,0xb9fead7e,0x3ab53365,0xb85dbbc9,0x39ba28b6,0xb996bbff,
0x37b73b80,0x3b023593,0x3b1a3bc9,0x375eb365,0xba5eb2a1,0x38d83bd4,0xb53435f1,0x3b913b6e,0xb9babbfc,0xb996abd9,0xbbddbae9,0xb1db3807,0x38b0ad7e,0xba7cbbf8,0x28b6b900,0xbbffba3f,
0x385d3b91,0x3ab53534,0x3c003a5e,0x2248b8d8,0xb972ad7e,0x39dc3bf8,0x33653a3f,0x3bc93900,0xbb02bbe6,0xb7b73115,0xbb1ab6aa,0x375e3b46,0x3414b64e,0xbbbcbb5a,0xb94dbbdd,0xb9feb1db,
0x38d83ba0,0x3a5e34d5,0x3b3037b7,0xb705bb02,0xb85d28b6,0x3ab53bff,0x39ba3be6,0x39963115,0xbbc9bb6e,0xb36535f1,0xb6aa31db,0x3b463bdd,0xaf0eb94d,0xbbf4b9fe,0xbbf8bae9,0xad7e3807,
0x394d3baf,0x39fe3475,0x38d82d7e,0xba5ebbf8,0xb64e3115,0x3b5a3be6,0x3bd43b80,0x32a1b593,0xbbffba99,0x28b63887,0x336539ba,0x3bc93996,0xb75ebae9,0xbb1ab807,0xba3fb534,0x39003b91,
0x39ba3bbc,0x39963414,0x31dbb534,0xbbddbb91,0xb3653475,0x3bc93baf,0x3b803927,0xb593ba1f,0xbba0b972,0x34d539dc,0x3a3f3be6,0x39003115,0xb9febbd4,0xb94db2a1,0xb04e35f1,0x3bed3b6e,
0x3a1f3bc9,0x39273365,0xb475b972,0xbbafb9dc,0xabd9364e,0x3bfc3b5a,0x38d831db,0xba5ebbdd,0xbab5b807,0x385d3ae9,0x3c003b30,0x2248b705,0xbb80bbf4,0xb5932f0e,0x38b03b1a,0x3a7c375e,
0x3a7c3bd4,0x38b032a1,0xb972bb5a,0xb9dcb64e,0x2f0e3807,0x3bf43ae9,0x2d7eb534,0xbbf8bb91,0xb94db4d5,0x39fe3ba0,0x3a5e37b7,0xb8d8bb02,0xbc00bb46,0x224836aa,0x3bdd3bc9,0x31dbb365,
0x3ad03bdd,0x383231db,0xbb80bc00,0xb5932248,0x347538d8,0x3baf3a5e,0xb75eb9fe,0xbb1ab94d,0xb705ad7e,0x3b303bf8,0x3414af0e,0xbbbcbbf4,0xbb6eb9dc,0x35f13972,0x3ab538b0,0xb85dba7c,
0x3b1a3be6,0x375e3115,0xbbf4bb46,0x2f0e36aa,0x37053996,0x3b3039ba,0xbae9bbd4,0xb807b2a1,0xb1db304e,0x3bdd3bed,0xb64eb94d,0xbb5ab9fe,0xb9dcb7b7,0x39723b02,0x3365ad7e,0xbbc9bbf8,
0x3b5a3bed,0x364e304e,0xbab5b94d,0x385d39fe,0x38b03a3f,0x3a7c3900,0xbbffbba0,0x28b634d5,0x2d7e3593,0x3bf83b80,0xbb02bbc9,0xb7b7b365,0xb705b1db,0x3b303bdd,0xb807b9ba,0xbae9b996,
0x3b913bf4,0x35342f0e,0xb807b4d5,0x3ae93ba0,0x39ba3ad0,0x39963832,0xba99b972,0x388739dc,0x3593385d,0x3b803ab5,0xbbe6bb6e,0x311535f1,0xad7e304e,0x3bf83bed,0xbbafbbfc,0xb475abd9,
0x3bbc3bf8,0x34142d7e,0xabd92f0e,0x3bfc3bf4,0x3a993b46,0x388736aa,0xb64eb365,0x3b5a3bc9,0x38b039ba,0x3a7c3996,0xb972b85d,0x39dc3ab5,0x34753705,0x3baf3b30,0xbb1aba5e,0x375e38d8,
0x3bdd3bfc,0x31db2bd9,0x364e3807,0x3b5a3ae9,0x3b463ba0,0x36aa34d5,0x31153475,0x3be63baf,0x3a3f3ad0,0x39003832,0xad7e28b6,0x3bf83bff,0x38d83996,0x3a5e39ba,0xb534b2a1,0x3b913bd4,
0x3bf43bff,0x2f0e28b6,0x3a1f3a7c,0x392738b0,0x3bbc3bdd,0x341431db,0x394d39ba,0x39fe3996,0x3b5a3b91,0x364e3534,0x385d38d8,0x3ab53a5e,0x3ad03b1a,0x3832375e,0x36aa37b7,0x3b463b02,
0x3bff3c00,0x28b62248,0x3bc93bd4,0x336532a1,0x3bf83bfc,0x2d7e2bd9,0x3baf3bbc,0x34753414,0x3bed3bf4,0x304e2f0e,0x3b913ba0,0x353434d5,0x3bdd3be6,0x31db3115,0x3b6e3b80,0x35f13593,
0xb5933b6e,0x3b8035f1,0xb1153bdd,0x3be631db,0x34d5bb91,0xbba0b534,0x2f0ebbed,0xbbf4b04e,0xb4143baf,0x3bbc3475,0xabd93bf8,0x3bfc2d7e,0x32a1bbc9,0xbbd4b365,0x2248bbff,0xbc00a8b6,
0x37b73b46,0x3b02b6aa,0x3b1a3832,0x375ebad0,0xb8d8bab5,0xba5e385d,0xbb91b64e,0xb5343b5a,0x39ba39fe,0x3996b94d,0x3bdd3414,0x31dbbbbc,0xba7cb927,0xb8b03a1f,0xbbffaf0e,0xa8b63bf4,
0x3bd43534,0x32a1bb91,0x39bab8d8,0xb996ba5e,0xbbffad7e,0x28b63bf8,0xb8323a3f,0x3ad03900,0x3bafb115,0xb475bbe6,0x34d5bb46,0xbba0b6aa,0xbae9364e,0x38073b5a,0xabd93bdd,0x3bfc31db,
0x3a5eb75e,0xb8d8bb1a,0xb705bbaf,0xbb303475,0xb85d39dc,0x3ab53972,0x39ba3a7c,0x3996b8b0,0x3365bb5a,0xbbc9b64e,0xbb46b887,0xb6aa3a99,0x2f0e3bfc,0x3bf42bd9,0x3bf83414,0x2d7ebbbc,
0x2bd9bbaf,0xbbfcb475,0xbbedad7e,0x304e3bf8,0x35f13be6,0x3b6eb115,0x3ab5b593,0xb85dbb80,0xb9dcba99,0xb9723887,0xb83239ba,0x3ad03996,0x3ba03807,0x34d5bae9,0x2f0ebb91,0xbbf4b534,
0xb9babae9,0xb9963807,0xb1db3b30,0x3bdd3705,0x3bc937b7,0x3365bb02,0xb593bbf8,0xbb802d7e,0xbba028b6,0x34d53bff,0x3a3f3a7c,0x3900b8b0,0x394db85d,0xb9febab5,0xbbedb64e,0xb04e3b5a,
0xbbf8b365,0x2d7e3bc9,0x3b0239dc,0x37b7b972,0x39feb64e,0xb94dbb5a,0xbbedb1db,0x304e3bdd,0xb2a13ae9,0x3bd43807,0x39bab705,0xb996bb30,0xb6aabbf4,0xbb462f0e,0xb1153b1a,0x3be6375e,
0xb8b0385d,0x3a7c3ab5,0x39dcb5f1,0xb972bb6e,0xaf0ebbbc,0xbbf4b414,0xad7e3b30,0x3bf83705,0x39fe3b1a,0x394db75e,0xb8d8bbaf,0xba5e3475,0xbc00b593,0x22483b80,0x3bdd3832,0x31dbbad0,
0x33653bdd,0x3bc931db,0xb6aabc00,0xbb462248,0xbb02ba5e,0xb7b738d8,0x3ba0394d,0x34d5b9fe,0x3b912d7e,0xb534bbf8,0xbae92f0e,0x38073bf4,0xb64e3972,0x3b5a39dc,0x32a1ba7c,0xbbd4b8b0,
0x3b1a3a7c,0x375eb8b0,0xbbf4b593,0x2f0e3b80,0xbb30a248,0x37053c00,0x3807b85d,0xbae9bab5,0x31dbba5e,0xbbddb8d8,0x364e3bfc,0x3b5a2bd9,0x39723baf,0x39dcb475,0xbbc9b927,0xb3653a1f,
0x3b6e304e,0xb5f1bbed,0xb2a139fe,0x3bd4394d,0xb1153a3f,0x3be63900,0xb9dcbba0,0xb97234d5,0xba1fbb80,0xb9273593,0x3baf3365,0xb475bbc9,0x3b9131db,0xb534bbdd,0xb41439ba,0x3bbc3996,
0x3534b900,0xbb91ba3f,0x3ae93b1a,0x3807b75e,0x39ba3bc9,0x3996b365,0xba9928b6,0x38873bff,0xbb80b2a1,0x35933bd4,0xb115bb5a,0xbbe6b64e,0x2d7eba5e,0xbbf8b8d8,0x3baf39fe,0x3475b94d,
0xb807bbf8,0xbae9ad7e,0x39feaf0e,0xb94dbbf4,0x3bdd36aa,0xb1dbbb46,0x35f13bc9,0x3b6e3365,0xb11539ba,0x3be63996,0xbbffb85d,0x28b63ab5,0xbb02bb30,0xb7b73705,0x34d5b8d8,0xbba0ba5e,
0xbbddb9fe,0xb1db394d,0xb64ebbbc,0xbb5ab414,0x36aab75e,0xbb46bb1a,0x3be637b7,0xb115bb02,0x3a3f3bc9,0x3900b365,0xad7e39dc,0x3bf83972,0xba5ea248,0x38d83c00,0xbb91bab5,0xb534385d,
0xba3fa8b6,0x39003bff,0xbbf8b8b0,0x2d7e3a7c,0xb807bbdd,0xbae9b1db,0x2bd9b9ba,0xbbfcb996,0x3b6e3534,0xb5f1bb91,0x3bd43a5e,0x32a1b8d8,0x33653b1a,0x3bc9375e,0xb59337b7,0x3b803b02,
0xa8b63996,0x3bff39ba,0xb365385d,0x3bc93ab5,0xbbf8b9fe,0xad7e394d,0xbbafbae9,0xb4753807,0x304eb900,0xbbedba3f,0x3534b75e,0xbb91bb1a,0x3bdd3a7c,0x31dbb8b0,0x3b6e3b46,0x35f1b6aa,
0x39dc3c00,0x3972a248,0x3ad03bd4,0x3832b2a1,0xb9272bd9,0x3a1f3bfc,0xb7b73414,0x3b023bbc,0xba5ebbf4,0xb8d82f0e,0xbb30bba0,0xb70534d5,0x3887b115,0xba99bbe6,0x364eb593,0xbb5abb80,
0x3bf43972,0xaf0eb9dc,0x3a1f3115,0xb927bbe6,0x34143a99,0x3bbc3887,0x39fe3c00,0x394d2248,0xbb5ab705,0x364e3b30,0xb85d304e,0x3ab53bed,0xb832bba0,0xbad0b4d5,0xbb46bbaf,0xb6aa3475,
0x3887abd9,0xba99bbfc,0xb5f1bae9,0xbb6eb807,0x3b803ba0,0x3593b4d5,0x3a7c3475,0xb8b0bbaf,0xaf0e3832,0x3bf43ad0,0x3a1f3bff,0x392728b6,0xbbedb996,0x304e39ba,0xb70532a1,0x3b303bd4,
0xb414ba1f,0xbbbcb927,0xbbfcba3f,0x2bd93900,0x3a993593,0xb887bb80,0xb64ebad0,0xbb5ab832,0x3a7c3c00,0x38b02248,0x39dc32a1,0xb972bbd4,0xb4753534,0x3baf3b91,0x3b1a3bed,0x375eb04e,
0xbb30bbf4,0xb7052f0e,0xb41434d5,0x3bbc3ba0,0x2248b832,0xbc00bad0,0xbbddb9dc,0x31db3972,0x3b46385d,0xb6aabab5,0xb8b0bb6e,0xba7cb5f1,0x3a1f3bed,0x3927304e,0x37b7abd9,0xbb02bbfc,
0xbb5ab8d8,0x364e3a5e,0x3ab53bfc,0x385d2bd9,0xba7cbbf4,0xb8b0af0e,0xa8b6375e,0x3bff3b1a,0x2d7eb6aa,0xbbf8bb46,0xbb02b832,0x37b73ad0,0x3b303887,0xb705ba99,0xbae9bc00,0xb807a248,
0xb4d53115,0x3ba03be6,0x3a3f36aa,0xb900bb46,0xbb91b996,0x353439ba,0x3bbc3bd4,0x3414b2a1,0xba99bbed,0xb887b04e,0x35f139fe,0x3b6e394d,0xa8b6b7b7,0xbbffbb02,0xb832ad7e,0x3ad03bf8,
0x38323a99,0x3ad03887,0xb593b996,0xbb80b9ba,0xb475304e,0x3baf3bed,0x375e2bd9,0xbb1abbfc,0xbb30b927,0x37053a1f,0x3bbc3a3f,0xb414b900,0xbb6ebbff,0xb5f128b6,0x3ab53be6,0x385d3115,
0x3be63bd4,0x3115b2a1,0xbbffbb5a,0x28b6364e,0x39003ae9,0x3a3f3807,0xba1fbb91,0xb927b534,0xabd934d5,0x3bfc3ba0,0xb04eb7b7,0xbbedbb02,0xb9bab6aa,0x39963b46,0x38873365,0xba99bbc9,
0x3a1f3832,0xb927bad0,0xb47528b6,0x3baf3bff,0x3bfc3b6e,0xabd9b5f1,0xba5eb887,0x38d83a99,0x3ab53bbc,0x385d3414,0xbc00bb91,0x22483534,0x35933900,0x3b803a3f,0xba7cbba0,0xb8b0b4d5,
0x2248b414,0xbc00bbbc,0x3a993b91,0x38873534,0x38323475,0xbad0bbaf,0x36aa3927,0x3b463a1f,0x3b1a39dc,0xb75eb972,0xaf0e3115,0x3bf43be6,0x3bfc3bd4,0x2bd9b2a1,0xb8d8b5f1,0x3a5e3b6e,
0xb9febb02,0xb94db7b7,0x3a5e3927,0xb8d8ba1f,0xb64eb8b0,0xbb5aba7c,0x3bd43b46,0xb2a1b6aa,0x28b6b1db,0xbbffbbdd,0x3bc93c00,0x33652248,0x375e3414,0xbb1abbbc,0x3a3f3b30,0x39003705,
0xbbedbba0,0x304e34d5,0xb534b7b7,0xbb91bb02,0xbbd4bbff,0xb2a1a8b6,0x2248b115,0xbc00bbe6,0xbad0bb6e,0xb832b5f1,0x359331db,0xbb80bbdd,0xb900b9fe,0xba3fb94d,0x39273807,0xba1fbae9,
0xb85db705,0x3ab53b30,0xbc00bbed,0x2248304e,0xb9dcb927,0x39723a1f,0xbbc9bbf4,0xb365af0e,0xbb02ba7c,0x37b738b0,0xbb1abb80,0xb75eb593,0xbbbcbb6e,0x341435f1,0xb9feba99,0xb94db887,
0x34753593,0x3baf3b80,0xb4d5b365,0x3ba03bc9,0x304e32a1,0x3bed3bd4,0xb705b5f1,0x3b303b6e,0xa2482bd9,0x3c003bfc,0xb887b807,0x3a993ae9,0xb115ad7e,0x3be63bf8,0xb972b900,0x39dc3a3f,
0x3b463b5a,0x36aa364e,0x3a7c3a99,0x38b03887,0x3b1a3b30,0x375e3705,0x3a3f3a5e,0x390038d8,0x3ae93b02,0x380737b7,0x39fe3a1f,0x394d3927,0x3ab53ad0,0x385d3832,0x39ba39dc,0x39963972,
0x28b63c00,0x3bffa248,0x33653bd4,0x3bc9b2a1,0xad7ebbfc,0xbbf82bd9,0xb475bbbc,0xbbaf3414,0x304e3bf4,0x3bedaf0e,0x35343ba0,0x3b91b4d5,0xb1dbbbe6,0xbbdd3115,0xb5f1bb80,0xbb6e3593,
0x3bf4a8b6,0xaf0ebbff,0x3a1fb8b0,0xb927ba7c,0xbbbc31db,0x34143bdd,0xb94d3996,0x39fe39ba,0x3b5ab534,0xb64ebb91,0x385dba5e,0xbab5b8d8,0xbad0375e,0x38323b1a,0xb6aa3b02,0x3b4637b7,
0xb1dbbbfc,0xbbdd2bd9,0xbb5ab807,0xb64e3ae9,0x36aa3ba0,0x3b46b4d5,0x3be63475,0x3115bbaf,0xb900bad0,0xba3f3832,0xbbf8a8b6,0x2d7e3bff,0x3a5e3996,0x38d8b9ba,0x3b91b2a1,0xb534bbd4,
0xbbbc2d7e,0x34143bf8,0x2bd93bf4,0x3bfc2f0e,0x3a99b6aa,0xb887bb46,0xb64ebbc9,0xbb5a3365,0xb8b03996,0x3a7c39ba,0x39723ab5,0x39dcb85d,0x3475bb30,0xbbafb705,0xbb1ab8d8,0xb75e3a5e,
0x35343bf4,0x3b91af0e,0x3ae9b4d5,0xb807bba0,0xb996bad0,0xb9ba3832,0xb8873972,0x3a9939dc,0x3b80385d,0x3593bab5,0x3115bb6e,0xbbe6b5f1,0xbbf8b04e,0x2d7e3bed,0x34753bfc,0x3bafabd9,
0x3b5ab04e,0xb64ebbed,0xbab5b9fe,0xb85d394d,0xb8b03900,0x3a7c3a3f,0x3bff34d5,0x28b6bba0,0x2d7ebb80,0xbbf8b593,0xbb023365,0x37b73bc9,0x37053bdd,0x3b30b1db,0x3807b996,0xbae9b9ba,
0xb75ebbe6,0xbb1a3115,0xaf0e3b46,0x3bf436aa,0x3b303996,0x3705b9ba,0xb807bbd4,0xbae932a1,0xbbddb04e,0x31db3bed,0x3b5a394d,0x364eb9fe,0x3972b7b7,0xb9dcbb02,0xbbc9ad7e,0x33653bf8,
0xbad031db,0x38323bdd,0x3b802248,0xb593bc00,0x3475ba5e,0xbbafb8d8,0xb75e394d,0x3b1a39fe,0x37053bf8,0x3b30ad7e,0xb414bbf4,0xbbbcaf0e,0xbb6eb972,0xb5f139dc,0x3ab53a7c,0x385db8b0,
0x38b03bd4,0x3a7cb2a1,0xb9dcbb5a,0xb972364e,0xbbf4b807,0xaf0e3ae9,0x3bf83534,0xad7ebb91,0x39feb4d5,0xb94dbba0,0xb8d837b7,0x3a5e3b02,0xa2483b46,0x3c0036aa,0xb1dbbbc9,0xbbddb365,
0x3a1fb365,0xb927bbc9,0xb47539dc,0x3baf3972,0x2bd93b5a,0x3bfc364e,0xb8d8bbdd,0xba5e31db,0xbab5bae9,0xb85d3807,0x3c003705,0xa248bb30,0x3b802f0e,0xb593bbf4,0xb8b0375e,0x3a7c3b1a,
0xb996bbbc,0xb9ba3414,0x3bdd3534,0xb1dbbb91,0x3bc93475,0xb365bbaf,0xb5933927,0x3b803a1f,0xb4d53972,0x3ba039dc,0xb900bbe6,0xba3f3115,0xb94dbbd4,0xb9fe32a1,0x3bed35f1,0xb04ebb6e,
0xb94d3475,0x39fe3baf,0xb8d8bbf8,0xba5e2d7e,0xb64ebbe6,0xbb5ab115,0x3bd43593,0xb2a1bb80,0x3bff3887,0x28b6ba99,0xb3653996,0x3bc939ba,0xb75e3807,0x3b1a3ae9,0xba3fbb91,0xb9003534,
0x3a5e3ba0,0x38d8b4d5,0xb70537b7,0x3b303b02,0xbab5a8b6,0x385d3bff,0xb996bbe6,0xb9ba3115,0xb365bb6e,0xbbc9b5f1,0x3b4631db,0xb6aabbdd,0x3bf4394d,0x2f0eb9fe,0x2d7e3ae9,0x3bf83807,
0x385db534,0xbab5bb91,0x3c0038d8,0xa248ba5e,0x39723bf8,0x39dcad7e,0xb3653900,0x3bc93a3f,0xbb02b115,0x37b73be6,0xbb1abb46,0xb75e36aa,0xb414bb5a,0xbbbcb64e,0x394db1db,0xb9febbdd,
0xbb02bb80,0xb7b73593,0xb75ebbc9,0xbb1ab365,0x38d8b2a1,0xba5ebbd4,0x3b9135f1,0xb534bb6e,0x39963bfc,0x39baabd9,0x31db3ae9,0x3bdd3807,0xba7cad7e,0x38b03bf8,0xbbffb900,0x28b63a3f,
0xb6aa35f1,0x3b463b6e,0xb8b031db,0x3a7c3bdd,0xbb1abb91,0xb75e3534,0xba3fbbed,0xb900304e,0x3807b475,0xbae9bbaf,0x394dad7e,0xb9febbf8,0x3ab53bc9,0x385db365,0x39ba3bff,0x3996a8b6,
0x3b803b5a,0x3593b64e,0x3be63a99,0x3115b887,0xb4d53705,0x3ba03b30,0xaf0e38d8,0x3bf43a5e,0xbbbcbb02,0xb41437b7,0xbbfcba1f,0xabd93927,0x32a1b832,0xbbd4bad0,0x2248b972,0xbc00b9dc,
0x3475b6aa,0xbbafbb46,0xb4d5bad0,0xbba0b832,0x3bed3ab5,0x304eb85d,0x3b30364e,0xb705bb5a,0x2248394d,0x3c0039fe,0x38873bbc,0x3a993414,0xbbe6b927,0x31153a1f,0xb9dcaf0e,0x39723bf4,
0xbbd4bb30,0xb2a13705,0xb9bab04e,0x39963bed,0xa8b6b927,0xbbffba1f,0xbad0bbf4,0xb8322f0e,0x3baf38b0,0xb475ba7c,0x34d5b593,0xbba0bb80,0x38073b6e,0x3ae935f1,0x3bfc3a99,0x2bd9b887,
0xb04e375e,0x3bed3b1a,0x3b913baf,0x3534b475,0xbbd4b972,0x32a139dc,0x224838b0,0x3c003a7c,0xb832bb5a,0xbad0b64e,0xbb80b887,0x35933a99,0x39002bd9,0xba3fbbfc,0xb927bbbc,0xba1fb414,
0x3bfc3b02,0x2bd9b7b7,0xb04eb927,0xbbedba1f,0x35f13a7c,0x3b6e38b0,0x3ab536aa,0xb85dbb46,0xb972b1db,0x39dc3bdd,0x3ad03c00,0x3832a248,0xbba0bbbc,0xb4d53414,0xaf0e3705,0x3bf43b30,
0xa248b807,0xbc00bae9,0xba99b705,0x38873b30,0x3ad037b7,0xb832bb02,0xbb46bbf8,0xb6aa2d7e,0x3b1a3bff,0x375ea8b6,0xaf0eb8b0,0xbbf4ba7c,0x2bd9385d,0x3bfc3ab5,0x3a5e364e,0xb8d8bb5a,
0xbbf8bad0,0x2d7e3832,0x3b023bff,0x37b728b6,0xb94dbb6e,0xb9feb5f1,0x304e3887,0x3bed3a99,0x32a1b414,0xbbd4bbbc,0xb9bab534,0x39963b91,0x3b463900,0xb6aaba3f,0xbbe6bba0,0xb11534d5,
0x3115385d,0x3be63ab5,0x28b6b5f1,0xbbffbb6e,0xb900b414,0x3a3f3bbc,0x3a1f3705,0xb927bb30,0xbbfcbb1a,0x2bd9375e,0x3bed3baf,0x304eb475,0xb9babb80,0xb996b593,0x38873ad0,0x3a993832,
0x3bc93a99,0xb365b887,0xbb46b996,0x36aa39ba,0x3b023bed,0x37b7304e,0xbba0bbfc,0xb4d52bd9,0x35343927,0x3b913a1f,0xb807ba3f,0xbae9b900,0xb64ea8b6,0x3b5a3bff,0x32a1b115,0xbbd4bbe6,
0xb4d5b8b0,0xbba0ba7c,0x3a3f3b80,0x39003593,0x35342248,0xbb91bc00,0x3414385d,0x3bbc3ab5,0x3a9938d8,0xb887ba5e,0xb5f1abd9,0x3b6e3bfc,0x3bff3baf,0x28b6b475,0xbad0b927,0x38323a1f,
0xbb6eba5e,0x35f138d8,0x32a1abd9,0xbbd4bbfc,0xbbe6bbf4,0xb1152f0e,0x3972375e,0xb9dcbb1a,0xba1fbb46,0xb927b6aa,0x3baf3ad0,0xb475b832,0xb534b887,0xbb91ba99,0x3bbc3c00,0x3414a248,
0x37053900,0x3b303a3f,0xbbbcbb1a,0x3414375e,0x22483365,0x3c003bc9,0xbbddbbff,0xb1db28b6,0xb6aab2a1,0x3b463bd4,0xba7cbb5a,0xb8b0b64e,0xba1fb8d8,0x39273a5e,0xb7b7b94d,0xbb02b9fe,
0x3ae93a1f,0xb807b927,0x394d3a3f,0x39fe3900,0x3bdd3b80,0xb1dbb593,0x35f13832,0x3b6e3ad0,0x3be63c00,0x3115a248,0x28b632a1,0x3bff3bd4,0x3b023b91,0x37b73534,0xb4d5b04e,0x3ba03bed,
0xb887b94d,0xba99b9fe,0x35f13414,0xbb6ebbbc,0xb593b75e,0xbb80bb1a,0x38b037b7,0xba7cbb02,0xaf0eb365,0xbbf4bbc9,0x3a1f3972,0xb927b9dc,0x304e2248,0xbbedbc00,0x3b303ab5,0xb705b85d,
0xba3fb9dc,0x39003972,0xbbf8bbe6,0x2d7e3115,0xbae9ba99,0x38073887,0xbbfcbc00,0xabd92248,0xbb6ebb30,0x35f13705,0xbbd4bbed,0xb2a1b04e,0xbbc9bba0,0x336534d5,0xbb80bbaf,0xb593b475,
0x39723996,0x39dc39ba,0x3832385d,0x3ad03ab5,0x3927394d,0x3a1f39fe,0x37b73807,0x3b023ae9,0x38d83900,0x3a5e3a3f,0x3705375e,0x3b303b1a,0x388738b0,0x3a993a7c,0x364e36aa,0x3b5a3b46,
0x36aa3b5a,0x3b46b64e,0x38b03a99,0x3a7cb887,0xb75ebb30,0xbb1a3705,0xb900ba5e,0xba3f38d8,0x38073b02,0x3ae9b7b7,0x394d3a1f,0x39feb927,0xb85dbad0,0xbab53832,0xb996b9dc,0xb9ba3972,
0x3475bb80,0xbbafb593,0xb4d5bbc9,0xbba03365,0xb04e3bd4,0x3bed32a1,0x37053b6e,0x3b30b5f1,0xa248bbfc,0xbc00abd9,0xb887bae9,0xba993807,0x31153bf8,0x3be6ad7e,0x39723a3f,0x39dcb900,
0xbab53705,0x385d3b30,0xa2483bed,0x3c00304e,0x3972b927,0xb9dcba1f,0xb365bbf4,0xbbc92f0e,0xb7b73a7c,0x3b0238b0,0x375e3b80,0x3b1ab593,0x3414bb6e,0xbbbcb5f1,0xb94dba99,0xb9fe3887,
0x3bed34d5,0x304ebba0,0x3534bb02,0xbb91b7b7,0xbbd428b6,0x32a13bff,0x22483be6,0x3c003115,0x3ad0b5f1,0xb832bb6e,0xb593bbdd,0xbb8031db,0xb900394d,0x3a3f39fe,0x39273ae9,0x3a1fb807,
0xb94dbb02,0xb9fe37b7,0xb8d83927,0x3a5e3a1f,0x3b5a38b0,0x364eba7c,0x32a1bb46,0xbbd4b6aa,0xbbffb1db,0x28b63bdd,0x33653c00,0x3bc9a248,0x3b1ab414,0xb75ebbbc,0xb900bb30,0xba3f3705,
0x22483bbc,0x3c003414,0x3a99b534,0xb887bb91,0xb832bbaf,0xbad03475,0xb6aa3a1f,0x3b463927,0x3b1a3972,0x375eb9dc,0xaf0ebbe6,0xbbf4b115,0xbbfcb2a1,0x2bd93bd4,0x38d83b6e,0x3a5eb5f1,
0x3927b832,0xba1fbad0,0xbbafa8b6,0x34753bff,0xabd93b6e,0x3bfc35f1,0x38d8b887,0xba5eba99,0xb85dbbbc,0xbab53414,0xa2483b91,0x3c003534,0x3b803900,0x3593ba3f,0xb8b0bba0,0xba7c34d5,
0xbbe6b2a1,0x31153bd4,0x3bff364e,0x28b6bb5a,0x3900b807,0xba3fbae9,0xba1f3534,0x39273b91,0x2bd93ba0,0x3bfc34d5,0x304ebb02,0xbbedb7b7,0xb9babb46,0xb99636aa,0x38873bc9,0x3a99b365,
0x3ad03a99,0x3832b887,0xbb80b996,0xb59339ba,0xbbafb04e,0x34753bed,0x3b1aabd9,0xb75ebbfc,0x3705b927,0xbb30ba1f,0xb4143a3f,0x3bbc3900,0x35f13bff,0x3b6e28b6,0xb85dbbe6,0xbab53115,
0xb4d5bbe6,0xbba0b115,0x3a3f3b46,0x3900b6aa,0x3b9139ba,0x3534b996,0xbbbcb2a1,0x34143bd4,0xba99304e,0x38873bed,0x35f1b94d,0xbb6eb9fe,0x28b6bb02,0xbbffb7b7,0x38323bf8,0x3ad0ad7e,
0xb64e38d8,0x3b5a3a5e,0xb85dbbfc,0xbab52bd9,0xb8b0bbf4,0xba7c2f0e,0x3bff375e,0xa8b6bb1a,0x3bf836aa,0xad7ebb46,0xb7b73832,0x3b023ad0,0xb7053887,0x3b303a99,0xb807bc00,0xbae92248,
0x3b302f0e,0xb705bbf4,0x34143ba0,0x3bbc34d5,0x22483ad0,0x3c003832,0xbbddb972,0xb1db39dc,0xbb46bab5,0xb6aa385d,0x38b0b5f1,0xba7cbb6e,0x3a1fb04e,0xb927bbed,0x37b73bfc,0x3b022bd9,
0xbbbcba1f,0xb4143927,0x2bd9ba3f,0xbbfcb900,0x3887b593,0xba99bb80,0x3b5a3ad0,0x364eb832,0x38b03c00,0x3a7ca248,0xb97232a1,0x39dc3bd4,0xbbafb534,0x34753b91,0xb75ebbed,0xbb1ab04e,
0x38873bfc,0x3a992bd9,0xb5f13807,0x3b6e3ae9,0xbb80b4d5,0x35933ba0,0xba7cbbaf,0xb8b03475,0xaf0ebad0,0xbbf4b832,0x3a1fa8b6,0xb927bbff,0x3bed39ba,0x304eb996,0x37053bd4,0x3b3032a1,
0x2f0eb972,0xbbf4b9dc,0x3927b115,0xba1fbbe6,0x3bbc3a99,0x3414b887,0x394d3c00,0x39fea248,0xb64e3705,0x3b5a3b30,0xbab5b04e,0x385d3bed,0xbad0bba0,0xb83234d5,0xb6aabbaf,0xbb46b475,
0xb9dca248,0x39723c00,0xbad0b2a1,0x38323bd4,0xb927bbfc,0xba1fabd9,0xb7b7bbbc,0xbb02b414,0x3a5e2f0e,0xb8d8bbf4,0x3b3034d5,0xb705bba0,0x38873be6,0x3a993115,0x364e3b80,0x3b5a3593,
0x3bff3996,0xa8b6b9ba,0x3bc9385d,0xb365bab5,0x2d7e39fe,0x3bf8394d,0x34753ae9,0x3baf3807,0xbbedb900,0x304e3a3f,0xbb91b75e,0x35343b1a,0xb1dbba7c,0xbbddb8b0,0xb5f1bb46,0xbb6eb6aa,
0xba3fbbff,0xb90028b6,0xbbf8ba7c,0xad7e38b0,0x3807b1db,0xbae9bbdd,0xabd9b996,0xbbfcb9ba,0x3b6e3b91,0x35f1b534,0x3bd438d8,0xb2a1ba5e,0xb365375e,0x3bc93b1a,0x35933b02,0x3b8037b7,
0x31db39fe,0x3bdd394d,0x3b5a3bbc,0x364eb414,0xbb46b75e,0x36aa3b1a,0xb11537b7,0x3be63b02,0xb900bbc9,0xba3fb365,0xbbf8b9dc,0x2d7e3972,0x38d8a248,0xba5ebc00,0xb534bab5,0xbb91b85d,
0x3807ad7e,0xbae9bbf8,0xb9febbf4,0xb94daf0e,0x3bdd3b46,0x31dbb6aa,0x35f1b365,0xbb6ebbc9,0x31153996,0x3be639ba,0x3bff3ab5,0x28b6b85d,0xbb02b705,0x37b73b30,0x34d53a5e,0x3ba038d8,
0xbb91b900,0x35343a3f,0x38073b1a,0x3ae9375e,0xb996bbc9,0xb9bab365,0xb887a8b6,0x3a993bff,0x3593b2a1,0xbb80bbd4,0xbbe6bb5a,0xb115364e,0x3bf83a5e,0xad7eb8d8,0xb475b9fe,0xbbafb94d,
0x3b6e3bed,0x35f1b04e,0xb2a1b94d,0xbbd4b9fe,0x31153900,0x3be63a3f,0x39dc34d5,0xb972bba0,0xba1fb593,0x39273b80,0x3baf3bc9,0x3475b365,0xbb91bbdd,0xb53431db,0x34143996,0x3bbc39ba,
0xb75eba7c,0xbb1ab8b0,0xaf0e3593,0x3bf43b80,0x3705a248,0xbb30bc00,0xbae9b85d,0x38073ab5,0x3bdd3a5e,0xb1dbb8d8,0xbb5abbfc,0xb64e2bd9,0x39dc3baf,0x39723475,0xb365b927,0xbbc9ba1f,
0xb36531db,0x3bc93bdd,0x36aa2248,0xbb46bc00,0xbb02b8d8,0x37b73a5e,0x3ba039fe,0xb4d5b94d,0xbb91bbf8,0xb5342d7e,0x3ae93bf4,0x38072f0e,0xb64eb9dc,0xbb5ab972,0x32a138b0,0x3bd43a7c,
0x3a7c385d,0xb8b0bab5,0xb972b5f1,0x39dc3b6e,0x3bf43bbc,0x2f0eb414,0xbbf8bb30,0x2d7e3705,0x394d3b1a,0x39fe375e,0xba5ebbaf,0xb8d8b475,0xa2483593,0x3c003b80,0xb1dbb832,0xbbddbad0,
0xbbf8bbc9,0xad7e3365,0x3b023972,0xb7b7b9dc,0xb9febb5a,0xb94db64e,0x3bed3bdd,0x304eb1db,0xb2a1b807,0xbbd4bae9,0x39ba3b30,0x39963705,0x36aa2f0e,0xbb46bbf4,0x3115375e,0x3be63b1a,
0x39963ae9,0x39ba3807,0xbbddbb30,0x31db3705,0x336537b7,0x3bc93b02,0xbb80bbf8,0xb593ad7e,0xb4d5a8b6,0x3ba03bff,0xb900ba7c,0xba3fb8b0,0xb9feb85d,0x394d3ab5,0xb04eb64e,0xbbedbb5a,
0xabd9b475,0xbbfcbbaf,0x3bed3bf8,0x304ead7e,0x35f13115,0xbb6ebbe6,0x3ab53b80,0x385d3593,0x39dc3887,0xb972ba99,0x38323996,0x3ad039ba,0x3ba03ae9,0xb4d5b807,0x2f0e3534,0x3bf43b91,
0xb8d8b75e,0x3a5e3b1a,0xbb30bbaf,0xb705b475,0xbab5b9dc,0x385d3972,0xb996ba7c,0xb9bab8b0,0xbbc9bb5a,0x3365364e,0xb6aab887,0xbb46ba99,0xbbf4bbfc,0xaf0e2bd9,0xad7eb414,0xbbf8bbbc,
0x3bd43b91,0xb2a1b534,0x39ba3a5e,0x399638d8,0x3bff3bf8,0x28b6ad7e,0x38323900,0x3ad03a3f,0x3baf3be6,0x34753115,0x34d536aa,0x3ba03b46,0x3ae93b5a,0x3807364e,0x2bd931db,0x3bfc3bdd,
0xbb02bb46,0xb7b7b6aa,0xb75eb832,0xbb1abad0,0xba5ebab5,0xb8d8b85d,0xb534b64e,0xbb91bb5a,0xb996b9fe,0xb9bab94d,0xb1dbb414,0xbbddbbbc,0xb8b0b927,0xba7cba1f,0xa8b6af0e,0xbbffbbf4,
0x359335f1,0x3b803b6e,0x311531db,0x3be63bdd,0x34d53534,0x3ba03b91,0x2f0e304e,0x3bf43bed,0x34143475,0x3bbc3baf,0x2bd92d7e,0x3bfc3bf8,0x32a13365,0x3bd43bc9,0x224828b6,0x3c003bff,
0x40000,0x60002,0xc0008,0xe000a,0x380034,0x3a0036,0x40003c,0x42003e,0x6c0068,0x6e006a,0x740070,0x760072,0xa0009c,0xa2009e,0xa800a4,0xaa00a6,
0xd400d0,0xd600d2,0xdc00d8,0xde00da,0x1080104,0x10a0106,0x110010c,0x112010e,0x13c0138,0x13e013a,0x1440140,0x1460142,0x170016c,0x172016e,0x1780174,0x17a0176,
0x1a401a0,0x1a601a2,0x1ac01a8,0x1ae01aa,0x1d801d4,0x1da01d6,0x1e001dc,0x1e201de,0x20c0208,0x20e020a,0x2140210,0x2160212,0x240023c,0x242023e,0x2480244,0x24a0246,
0x2740270,0x2760272,0x27c0278,0x27e027a,0x2a802a4,0x2aa02a6,0x2b002ac,0x2b202ae,0x2dc02d8,0x2de02da,0x2e402e0,0x2e602e2,0x310030c,0x312030e,0x3180314,0x31a0316,
0x3440340,0x3460342,0x34c0348,0x34e034a,0x3780374,0x37a0376,0x380037c,0x382037e,0x3ac03a8,0x3ae03aa,0x3b403b0,0x3b603b2,0x3e003dc,0x3e203de,0x3e803e4,0x3ea03e6,
0x4140410,0x4160412,0x41c0418,0x41e041a,0x4480444,0x44a0446,0x450044c,0x452044e,0x47c0478,0x47e047a,0x4840480,0x4860482,0x4b004ac,0x4b204ae,0x4b804b4,0x4ba04b6,
0x4e404e0,0x4e604e2,0x4ec04e8,0x4ee04ea,0x5180514,0x51a0516,0x520051c,0x522051e,0x54c0548,0x54e054a,0x5540550,0x5560552,0x580057c,0x582057e,0x5880584,0x58a0586,
0x5b405b0,0x5b605b2,0x5bc05b8,0x5be05ba,0x5e805e4,0x5ea05e6,0x5f005ec,0x5f205ee,0x61c0618,0x61e061a,0x6240620,0x6260622,0x650064c,0x652064e,0x6580654,0x65a0656,
0x140010,0x160012,0x120010,0x440012,0x480044,0x4a0046,0x460044,0x780046,0x7c0078,0x7e007a,0x7a0078,0xac007a,0xb000ac,0xb200ae,0xae00ac,0xe000ae,
0xe400e0,0xe600e2,0xe200e0,0x11400e2,0x1180114,0x11a0116,0x1160114,0x1480116,0x14c0148,0x14e014a,0x14a0148,0x17c014a,0x180017c,0x182017e,0x17e017c,0x1b0017e,
0x1b401b0,0x1b601b2,0x1b201b0,0x1e401b2,0x1e801e4,0x1ea01e6,0x1e601e4,0x21801e6,0x21c0218,0x21e021a,0x21a0218,0x24c021a,0x250024c,0x252024e,0x24e024c,0x280024e,
0x2840280,0x2860282,0x2820280,0x2b40282,0x2b802b4,0x2ba02b6,0x2b602b4,0x2e802b6,0x2ec02e8,0x2ee02ea,0x2ea02e8,0x31c02ea,0x320031c,0x322031e,0x31e031c,0x350031e,
0x3540350,0x3560352,0x3520350,0x3840352,0x3880384,0x38a0386,0x3860384,0x3b80386,0x3bc03b8,0x3be03ba,0x3ba03b8,0x3ec03ba,0x3f003ec,0x3f203ee,0x3ee03ec,0x42003ee,
0x4240420,0x4260422,0x4220420,0x4540422,0x4580454,0x45a0456,0x4560454,0x4880456,0x48c0488,0x48e048a,0x48a0488,0x4bc048a,0x4c004bc,0x4c204be,0x4be04bc,0x4f004be,
0x4f404f0,0x4f604f2,0x4f204f0,0x52404f2,0x5280524,0x52a0526,0x5260524,0x5580526,0x55c0558,0x55e055a,0x55a0558,0x58c055a,0x590058c,0x592058e,0x58e058c,0x5c0058e,
0x5c405c0,0x5c605c2,0x5c205c0,0x5f405c2,0x5f805f4,0x5fa05f6,0x5f605f4,0x62805f6,0x62c0628,0x62e062a,0x62a0628,0x65c062a,0x660065c,0x662065e,0x65e065c,0x18065e,
0x180018,0x4c001a,0x1a0018,0x4c001a,0x4c004c,0x80004e,0x4e004c,0x80004e,0x800080,0xb40082,0x820080,0xb40082,0xb400b4,0xe800b6,0xb600b4,0xe800b6,
0xe800e8,0x11c00ea,0xea00e8,0x11c00ea,0x11c011c,0x150011e,0x11e011c,0x150011e,0x1500150,0x1840152,0x1520150,0x1840152,0x1840184,0x1b80186,0x1860184,0x1b80186,
0x1b801b8,0x1ec01ba,0x1ba01b8,0x1ec01ba,0x1ec01ec,0x22001ee,0x1ee01ec,0x22001ee,0x2200220,0x2540222,0x2220220,0x2540222,0x2540254,0x2880256,0x2560254,0x2880256,
0x2880288,0x2bc028a,0x28a0288,0x2bc028a,0x2bc02bc,0x2f002be,0x2be02bc,0x2f002be,0x2f002f0,0x32402f2,0x2f202f0,0x32402f2,0x3240324,0x3580326,0x3260324,0x3580326,
0x3580358,0x38c035a,0x35a0358,0x38c035a,0x38c038c,0x3c0038e,0x38e038c,0x3c0038e,0x3c003c0,0x3f403c2,0x3c203c0,0x3f403c2,0x3f403f4,0x42803f6,0x3f603f4,0x42803f6,
0x4280428,0x45c042a,0x42a0428,0x45c042a,0x45c045c,0x490045e,0x45e045c,0x490045e,0x4900490,0x4c40492,0x4920490,0x4c40492,0x4c404c4,0x4f804c6,0x4c604c4,0x4f804c6,
0x4f804f8,0x52c04fa,0x4fa04f8,0x52c04fa,0x52c052c,0x560052e,0x52e052c,0x560052e,0x5600560,0x5940562,0x5620560,0x5940562,0x5940594,0x5c80596,0x5960594,0x5c80596,
0x5c805c8,0x5fc05ca,0x5ca05c8,0x5fc05ca,0x5fc05fc,0x63005fe,0x5fe05fc,0x63005fe,0x6300630,0x6640632,0x6320630,0x6640632,0x6640664,0x1c0666,0x6660664,0x1c0666,
0x1c001c,0x50001e,0x1e001c,0x50001e,0x500050,0x840052,0x520050,0x840052,0x840084,0xb80086,0x860084,0xb80086,0xb800b8,0xec00ba,0xba00b8,0xec00ba,
0xec00ec,0x12000ee,0xee00ec,0x12000ee,0x1200120,0x1540122,0x1220120,0x1540122,0x1540154,0x1880156,0x1560154,0x1880156,0x1880188,0x1bc018a,0x18a0188,0x1bc018a,
0x1bc01bc,0x1f001be,0x1be01bc,0x1f001be,0x1f001f0,0x22401f2,0x1f201f0,0x22401f2,0x2240224,0x2580226,0x2260224,0x2580226,0x2580258,0x28c025a,0x25a0258,0x28c025a,
0x28c028c,0x2c0028e,0x28e028c,0x2c0028e,0x2c002c0,0x2f402c2,0x2c202c0,0x2f402c2,0x2f402f4,0x32802f6,0x2f602f4,0x32802f6,0x3280328,0x35c032a,0x32a0328,0x35c032a,
0x35c035c,0x390035e,0x35e035c,0x390035e,0x3900390,0x3c40392,0x3920390,0x3c40392,0x3c403c4,0x3f803c6,0x3c603c4,0x3f803c6,0x3f803f8,0x42c03fa,0x3fa03f8,0x42c03fa,
0x42c042c,0x460042e,0x42e042c,0x460042e,0x4600460,0x4940462,0x4620460,0x4940462,0x4940494,0x4c80496,0x4960494,0x4c80496,0x4c804c8,0x4fc04ca,0x4ca04c8,0x4fc04ca,
0x4fc04fc,0x53004fe,0x4fe04fc,0x53004fe,0x5300530,0x5640532,0x5320530,0x5640532,0x5640564,0x5980566,0x5660564,0x5980566,0x5980598,0x5cc059a,0x59a0598,0x5cc059a,
0x5cc05cc,0x60005ce,0x5ce05cc,0x60005ce,0x6000600,0x6340602,0x6020600,0x6340602,0x6340634,0x6680636,0x6360634,0x6680636,0x6680668,0x20066a,0x66a0668,0x20066a,
0x5d605d6,0x60a05d6,0x5d605d6,0x60a060a,0x60a060a,0x63e063e,0x60a060a,0x63e063e,0x63e063e,0x672063e,0x63e063e,0x6720672,0x6720672,0x280028,0x6720672,0x280028,
0x5060506,0x53a0506,0x5060506,0x53a053a,0x53a053a,0x56e056e,0x53a053a,0x56e056e,0x56e056e,0x5a2056e,0x56e056e,0x5a205a2,0x5a205a2,0x5d605d6,0x5a205a2,0x5d605d6,
0x4360436,0x46a0436,0x4360436,0x46a046a,0x46a046a,0x49e049e,0x46a046a,0x49e049e,0x49e049e,0x4d2049e,0x49e049e,0x4d204d2,0x4d204d2,0x5060506,0x4d204d2,0x5060506,
0x3660366,0x39a0366,0x3660366,0x39a039a,0x39a039a,0x3ce03ce,0x39a039a,0x3ce03ce,0x3ce03ce,0x40203ce,0x3ce03ce,0x4020402,0x4020402,0x4360436,0x4020402,0x4360436,
0x2960296,0x2ca0296,0x2960296,0x2ca02ca,0x2ca02ca,0x2fe02fe,0x2ca02ca,0x2fe02fe,0x2fe02fe,0x33202fe,0x2fe02fe,0x3320332,0x3320332,0x3660366,0x3320332,0x3660366,
0x1c601c6,0x1fa01c6,0x1c601c6,0x1fa01fa,0x1fa01fa,0x22e022e,0x1fa01fa,0x22e022e,0x22e022e,0x262022e,0x22e022e,0x2620262,0x2620262,0x2960296,0x2620262,0x2960296,
0xf600f6,0x12a00f6,0xf600f6,0x12a012a,0x12a012a,0x15e015e,0x12a012a,0x15e015e,0x15e015e,0x192015e,0x15e015e,0x1920192,0x1920192,0x1c601c6,0x1920192,0x1c601c6,
0x260026,0x5a0026,0x260026,0x5a005a,0x5a005a,0x8e008e,0x5a005a,0x8e008e,0x8e008e,0xc2008e,0x8e008e,0xc200c2,0xc200c2,0xf600f6,0xc200c2,0xf600f6,
0x5d405d4,0x60805d4,0x5d405d4,0x6080608,0x6080608,0x63c063c,0x6080608,0x63c063c,0x63c063c,0x670063c,0x63c063c,0x6700670,0x6700670,0x260026,0x6700670,0x260026,
0x5040504,0x5380504,0x5040504,0x5380538,0x5380538,0x56c056c,0x5380538,0x56c056c,0x56c056c,0x5a0056c,0x56c056c,0x5a005a0,0x5a005a0,0x5d405d4,0x5a005a0,0x5d405d4,
0x4340434,0x4680434,0x4340434,0x4680468,0x4680468,0x49c049c,0x4680468,0x49c049c,0x49c049c,0x4d0049c,0x49c049c,0x4d004d0,0x4d004d0,0x5040504,0x4d004d0,0x5040504,
0x3640364,0x3980364,0x3640364,0x3980398,0x3980398,0x3cc03cc,0x3980398,0x3cc03cc,0x3cc03cc,0x40003cc,0x3cc03cc,0x4000400,0x4000400,0x4340434,0x4000400,0x4340434,
0x2940294,0x2c80294,0x2940294,0x2c802c8,0x2c802c8,0x2fc02fc,0x2c802c8,0x2fc02fc,0x2fc02fc,0x33002fc,0x2fc02fc,0x3300330,0x3300330,0x3640364,0x3300330,0x3640364,
0x1c401c4,0x1f801c4,0x1c401c4,0x1f801f8,0x1f801f8,0x22c022c,0x1f801f8,0x22c022c,0x22c022c,0x260022c,0x22c022c,0x2600260,0x2600260,0x2940294,0x2600260,0x2940294,
0xf400f4,0x12800f4,0xf400f4,0x1280128,0x1280128,0x15c015c,0x1280128,0x15c015c,0x15c015c,0x190015c,0x15c015c,0x1900190,0x1900190,0x1c401c4,0x1900190,0x1c401c4,
0x240024,0x580024,0x240024,0x580058,0x580058,0x8c008c,0x580058,0x8c008c,0x8c008c,0xc0008c,0x8c008c,0xc000c0,0xc000c0,0xf400f4,0xc000c0,0xf400f4,
0x5d205d2,0x60605d2,0x5d205d2,0x6060606,0x6060606,0x63a063a,0x6060606,0x63a063a,0x63a063a,0x66e063a,0x63a063a,0x66e066e,0x66e066e,0x240024,0x66e066e,0x240024,
0x5020502,0x5360502,0x5020502,0x5360536,0x5360536,0x56a056a,0x5360536,0x56a056a,0x56a056a,0x59e056a,0x56a056a,0x59e059e,0x59e059e,0x5d205d2,0x59e059e,0x5d205d2,
0x4320432,0x4660432,0x4320432,0x4660466,0x4660466,0x49a049a,0x4660466,0x49a049a,0x49a049a,0x4ce049a,0x49a049a,0x4ce04ce,0x4ce04ce,0x5020502,0x4ce04ce,0x5020502,
0x3620362,0x3960362,0x3620362,0x3960396,0x3960396,0x3ca03ca,0x3960396,0x3ca03ca,0x3ca03ca,0x3fe03ca,0x3ca03ca,0x3fe03fe,0x3fe03fe,0x4320432,0x3fe03fe,0x4320432,
0x2920292,0x2c60292,0x2920292,0x2c602c6,0x2c602c6,0x2fa02fa,0x2c602c6,0x2fa02fa,0x2fa02fa,0x32e02fa,0x2fa02fa,0x32e032e,0x32e032e,0x3620362,0x32e032e,0x3620362,
0x1c201c2,0x1f601c2,0x1c201c2,0x1f601f6,0x1f601f6,0x22a022a,0x1f601f6,0x22a022a,0x22a022a,0x25e022a,0x22a022a,0x25e025e,0x25e025e,0x2920292,0x25e025e,0x2920292,
0xf200f2,0x12600f2,0xf200f2,0x1260126,0x1260126,0x15a015a,0x1260126,0x15a015a,0x15a015a,0x18e015a,0x15a015a,0x18e018e,0x18e018e,0x1c201c2,0x18e018e,0x1c201c2,
0x220022,0x560022,0x220022,0x560056,0x560056,0x8a008a,0x560056,0x8a008a,0x8a008a,0xbe008a,0x8a008a,0xbe00be,0xbe00be,0xf200f2,0xbe00be,0xf200f2,
0x5d005d0,0x60405d0,0x5d005d0,0x6040604,0x6040604,0x6380638,0x6040604,0x6380638,0x6380638,0x66c0638,0x6380638,0x66c066c,0x66c066c,0x220022,0x66c066c,0x220022,
0x5000500,0x5340500,0x5000500,0x5340534,0x5340534,0x5680568,0x5340534,0x5680568,0x5680568,0x59c0568,0x5680568,0x59c059c,0x59c059c,0x5d005d0,0x59c059c,0x5d005d0,
0x4300430,0x4640430,0x4300430,0x4640464,0x4640464,0x4980498,0x4640464,0x4980498,0x4980498,0x4cc0498,0x4980498,0x4cc04cc,0x4cc04cc,0x5000500,0x4cc04cc,0x5000500,
0x3600360,0x3940360,0x3600360,0x3940394,0x3940394,0x3c803c8,0x3940394,0x3c803c8,0x3c803c8,0x3fc03c8,0x3c803c8,0x3fc03fc,0x3fc03fc,0x4300430,0x3fc03fc,0x4300430,
0x2900290,0x2c40290,0x2900290,0x2c402c4,0x2c402c4,0x2f802f8,0x2c402c4,0x2f802f8,0x2f802f8,0x32c02f8,0x2f802f8,0x32c032c,0x32c032c,0x3600360,0x32c032c,0x3600360,
0x1c001c0,0x1f401c0,0x1c001c0,0x1f401f4,0x1f401f4,0x2280228,0x1f401f4,0x2280228,0x2280228,0x25c0228,0x2280228,0x25c025c,0x25c025c,0x2900290,0x25c025c,0x2900290,
0xf000f0,0x12400f0,0xf000f0,0x1240124,0x1240124,0x1580158,0x1240124,0x1580158,0x1580158,0x18c0158,0x1580158,0x18c018c,0x18c018c,0x1c001c0,0x18c018c,0x1c001c0,
0x200020,0x540020,0x200020,0x540054,0x540054,0x880088,0x540054,0x880088,0x880088,0xbc0088,0x880088,0xbc00bc,0xbc00bc,0xf000f0,0xbc00bc,0xf000f0,
0x30003000,0x30003000,0x30003000,0x30003000,0x30003000,0x30003000,0x30003000,0x30003000,0x0,0x0,0x0,0x0,0x0,0x0,0x0,0x0,
0x30003000,0x30003000,0x30003000,0x30003000,0x30003000,0x30003000,0x30003000,0x30003000,0x0,0x0,0x0,0x0,0x0,0x0,0x0,0x0,
0x2a1f2da8,0xaf64ada8,0xaa1fada8,0x2f642da8,0x2f643000,0xaa1f0000,0xaf64b000,0x2a1f8000,0x2f642da8,0x2a1f2da8,0xaf64ada8,0xaa1fada8,0x2a1f0000,0x2f643000,0xaa1f0000,0xaf64b000,
0x263e2c72,0xafd9aea7,0xa63eac72,0x2fd92ea7,0x2ea72fd9,0xac72a63e,0xaea7afd9,0x2c72263e,0x2fd92ea7,0x263e2c72,0xafd9aea7,0xa63eac72,0x2c72263e,0x2ea72fd9,0xac72a63e,0xaea7afd9,
0x2da80000,0xada80000,0x2da88000,0xada80000,0x2da83000,0xada8b000,0x2da83000,0xada8b000,0x2da83000,0xada8b000,0x2da83000,0xada8b000,0xada80000,0x2da88000,0xada80000,0x2da88000,
0x2f642a1f,0xaf64aa1f,0x2f642a1f,0xaf64aa1f,0x2a1f2f64,0xaa1faf64,0x2a1f2f64,0xaa1faf64,0x2a1f2f64,0xaa1faf64,0x2a1f2f64,0xaa1faf64,0xaf64aa1f,0x2f642a1f,0xaf64aa1f,0x2f642a1f,
0xaa1f2da8,0x2f642da8,0x2a1fada8,0xaf64ada8,0x2f640000,0xaa1fb000,0xaf640000,0x2a1f3000,0xaf64ada8,0xaa1f2da8,0x2f642da8,0x2a1fada8,0x2a1f3000,0x2f648000,0xaa1fb000,0xaf640000,
0xaea7263e,0x2c722fd9,0x2ea7a63e,0xac72afd9,0x2fd92c72,0x263eaea7,0xafd9ac72,0xa63e2ea7,0xac72afd9,0xaea7263e,0x2c722fd9,0x2ea7a63e,0xa63e2ea7,0x2fd92c72,0x263eaea7,0xafd9ac72,
0xada82da8,0xada82da8,0xada82da8,0xada82da8,0x2da8ada8,0x2da8ada8,0x2da8ada8,0x2da8ada8,0x2da82da8,0x2da82da8,0x2da82da8,0x2da82da8,0xada8ada8,0xada8ada8,0xada8ada8,0xada8ada8,
0x3000,0x3000,0x3000,0x80003000,0x8000b000,0x8000b000,0x8000b000,0x8000b000,0x30000000,0x30008000,0x30008000,0x30008000,0xb0000000,0xb0000000,0xb0000000,0xb0000000,
0x2ea7263e,0xac722fd9,0xaea7a63e,0x2c72afd9,0xafd92c72,0xa63eaea7,0x2fd9ac72,0x263e2ea7,0x2c72afd9,0x2ea7263e,0xac722fd9,0xaea7a63e,0x263e2ea7,0xafd92c72,0xa63eaea7,0x2fd9ac72,
0x2f64ada8,0x2a1f2da8,0xaf642da8,0xaa1fada8,0xaa1f3000,0xaf640000,0x2a1fb000,0x2f648000,0xaa1fada8,0x2f64ada8,0x2a1f2da8,0xaf642da8,0x2f640000,0xaa1f3000,0xaf640000,0x2a1fb000,
0xaa1f2f64,0x2a1faf64,0xaa1f2f64,0x2a1faf64,0x2f64aa1f,0xaf642a1f,0x2f64aa1f,0xaf642a1f,0xaf642a1f,0x2f64aa1f,0xaf642a1f,0x2f64aa1f,0xaa1f2f64,0x2a1faf64,0xaa1f2f64,0x2a1faf64,
0x2da80000,0xada80000,0x2da88000,0xada80000,0x2da8b000,0xada83000,0x2da8b000,0xada83000,0xada83000,0x2da8b000,0xada83000,0x2da8b000,0x2da88000,0xada80000,0x2da88000,0xada88000,
0xa63e2c72,0x2fd9aea7,0x263eac72,0xafd92ea7,0xaea72fd9,0x2c72a63e,0x2ea7afd9,0xac72263e,0xafd92ea7,0xa63e2c72,0x2fd9aea7,0x263eac72,0xac72263e,0xaea72fd9,0x2c72a63e,0x2ea7afd9,
0x2f64ada8,0x2a1fada8,0xaf642da8,0xaa1f2da8,0x2a1f0000,0x2f64b000,0xaa1f0000,0xaf643000,0xaa1f2da8,0x2f64ada8,0x2a1fada8,0xaf642da8,0xaf643000,0x2a1f8000,0x2f64b000,0xaa1f8000,
0xb0003000,0xb0003000,0xb0003000,0xb0003000,0xb0003000,0xb0003000,0xb0003000,0xb0003000,0x0,0x8000,0x8000,0x80008000,0x8000,0x8000,0x8000,0x8000,
0x80000000,0x80000000,0x80008000,0x80008000,0x80000000,0x80008000,0x80008000,0x80008000,0xb0003000,0xb0003000,0xb0003000,0xb0003000,0xb0003000,0xb0003000,0xb0003000,0xb0003000,
0xaa1f2da8,0x2f64ada8,0x2a1fada8,0xaf642da8,0xaf643000,0x2a1f0000,0x2f64b000,0xaa1f8000,0xaf642da8,0xaa1f2da8,0x2f64ada8,0x2a1fada8,0xaa1f0000,0xaf643000,0x2a1f0000,0x2f64b000,
0x2fd9aea7,0x263eac72,0xafd92ea7,0xa63e2c72,0x2c72a63e,0x2ea7afd9,0xac72263e,0xaea72fd9,0xa63e2c72,0x2fd9aea7,0x263eac72,0xafd92ea7,0xaea72fd9,0x2c72a63e,0x2ea7afd9,0xac72263e,
0xada80000,0x2da80000,0xada88000,0x2da80000,0xada83000,0x2da8b000,0xada83000,0x2da8b000,0xada83000,0x2da8b000,0xada83000,0x2da8b000,0x2da80000,0xada88000,0x2da88000,0xada88000,
0xaa1f2f64,0x2a1faf64,0xaa1f2f64,0x2a1faf64,0x2f64aa1f,0xaf642a1f,0x2f64aa1f,0xaf642a1f,0x2f64aa1f,0xaf642a1f,0x2f64aa1f,0xaf642a1f,0x2a1faf64,0xaa1f2f64,0x2a1faf64,0xaa1f2f64,
0x2a1f2da8,0xaf642da8,0xaa1fada8,0x2f64ada8,0xaf640000,0x2a1fb000,0x2f640000,0xaa1f3000,0x2f64ada8,0x2a1f2da8,0xaf642da8,0xaa1fada8,0xaa1f3000,0xaf648000,0x2a1fb000,0x2f640000,
0x2c72afd9,0x2ea7263e,0xac722fd9,0xaea7a63e,0x263e2ea7,0xafd92c72,0xa63eaea7,0x2fd9ac72,0xaea7a63e,0x2c72afd9,0x2ea7263e,0xac722fd9,0x2fd9ac72,0x263e2ea7,0xafd92c72,0xa63eaea7,
0x2da8ada8,0x2da8ada8,0x2da8ada8,0x2da8ada8,0xada82da8,0xada82da8,0xada82da8,0xada82da8,0x2da82da8,0x2da82da8,0x2da82da8,0x2da82da8,0xada8ada8,0xada8ada8,0xada8ada8,0xada8ada8,
0x80003000,0x80003000,0x80003000,0x3000,0xb000,0x8000b000,0xb000,0xb000,0xb0000000,0xb0008000,0xb0008000,0xb0008000,0x30000000,0x30000000,0x30000000,0x30008000,
0x2c722fd9,0x2ea7a63e,0xac72afd9,0xaea7263e,0x263eaea7,0xafd9ac72,0xa63e2ea7,0x2fd92c72,0xaea7263e,0x2c722fd9,0x2ea7a63e,0xac72afd9,0x2fd92c72,0x263eaea7,0xafd9ac72,0xa63e2ea7,
0xaf64ada8,0xaa1f2da8,0x2f642da8,0x2a1fada8,0x2a1f3000,0x2f648000,0xaa1fb000,0xaf648000,0x2a1fada8,0xaf64ada8,0xaa1f2da8,0x2f642da8,0xaf640000,0x2a1f3000,0x2f648000,0xaa1fb000,
0x2f642a1f,0xaf64aa1f,0x2f642a1f,0xaf64aa1f,0x2a1f2f64,0xaa1faf64,0x2a1f2f64,0xaa1faf64,0xaa1faf64,0x2a1f2f64,0xaa1faf64,0x2a1f2f64,0x2f642a1f,0xaf64aa1f,0x2f642a1f,0xaf64aa1f,
0xada80000,0x2da80000,0xada88000,0x2da88000,0xada8b000,0x2da83000,0xada8b000,0x2da83000,0x2da83000,0xada8b000,0x2da83000,0xada8b000,0xada88000,0x2da88000,0xada88000,0x2da80000,
0x2fd92ea7,0x263e2c72,0xafd9aea7,0xa63eac72,0x2c72263e,0x2ea72fd9,0xac72a63e,0xaea7afd9,0xa63eac72,0x2fd92ea7,0x263e2c72,0xafd9aea7,0xaea7afd9,0x2c72263e,0x2ea72fd9,0xac72a63e,
0xaf64ada8,0xaa1fada8,0x2f642da8,0x2a1f2da8,0xaa1f0000,0xaf64b000,0x2a1f0000,0x2f643000,0x2a1f2da8,0xaf64ada8,0xaa1fada8,0x2f642da8,0x2f643000,0xaa1f8000,0xaf64b000,0x2a1f0000,
0x80008000,0x80008000,0x80008000,0x80008000,0x80008000,0x80008000,0x80008000,0x80008000,0x30003000,0x30003000,0x30003000,0x30003000,0x30003000,0x30003000,0x30003000,0x30003000,
0x80008000,0x80008000,0x80008000,0x80008000,0x80008000,0x80008000,0x80008000,0x80008000,0x30003000,0x30003000,0x30003000,0x30003000,0x30003000,0x30003000,0x30003000,0x30003000,
0xaf64ada8,0xaa1fada8,0x2f642da8,0x2a1f2da8,0xaa1f8000,0xaf64b000,0x2a1f8000,0x2f643000,0x2a1f2da8,0xaf64ada8,0xaa1fada8,0x2f642da8,0x2f643000,0xaa1f0000,0xaf64b000,0x2a1f8000,
0xafd9aea7,0xa63eac72,0x2fd92ea7,0x263e2c72,0xac72a63e,0xaea7afd9,0x2c72263e,0x2ea72fd9,0x263e2c72,0xafd9aea7,0xa63eac72,0x2fd92ea7,0x2ea72fd9,0xac72a63e,0xaea7afd9,0x2c72263e,
0x2da83000,0xada8b000,0x2da83000,0xada8b000,0xada80000,0x2da88000,0xada80000,0x2da88000,0xada88000,0x2da88000,0xada80000,0x2da88000,0xada8b000,0x2da83000,0xada8b000,0x2da83000,
0x2a1f2f64,0xaa1faf64,0x2a1f2f64,0xaa1faf64,0xaf64aa1f,0x2f642a1f,0xaf64aa1f,0x2f642a1f,0xaf64aa1f,0x2f642a1f,0xaf64aa1f,0x2f642a1f,0xaa1faf64,0x2a1f2f64,0xaa1faf64,0x2a1f2f64,
0xaf64ada8,0xaa1f2da8,0x2f642da8,0x2a1fada8,0x2a1f3000,0x2f648000,0xaa1fb000,0xaf640000,0x2a1fada8,0xaf64ada8,0xaa1f2da8,0x2f642da8,0xaf648000,0x2a1f3000,0x2f648000,0xaa1fb000,
0xac72afd9,0xaea7263e,0x2c722fd9,0x2ea7a63e,0xa63e2ea7,0x2fd92c72,0x263eaea7,0xafd9ac72,0x2ea7a63e,0xac72afd9,0xaea7263e,0x2c722fd9,0xafd9ac72,0xa63e2ea7,0x2fd92c72,0x263eaea7,
0xada8ada8,0xada8ada8,0xada8ada8,0xada8ada8,0x2da82da8,0x2da82da8,0x2da82da8,0x2da82da8,0xada82da8,0xada82da8,0xada82da8,0xada82da8,0x2da8ada8,0x2da8ada8,0x2da8ada8,0x2da8ada8,
0xb0008000,0xb0000000,0xb0000000,0xb0000000,0x30008000,0x30008000,0x30008000,0x30008000,0x3000,0x3000,0x3000,0x80003000,0x8000b000,0x8000b000,0x8000b000,0x8000b000,
0xac722fd9,0xaea7a63e,0x2c72afd9,0x2ea7263e,0xa63eaea7,0x2fd9ac72,0x263e2ea7,0xafd92c72,0x2ea7263e,0xac722fd9,0xaea7a63e,0x2c72afd9,0xafd92c72,0xa63eaea7,0x2fd9ac72,0x263e2ea7,
0x2a1f2da8,0xaf642da8,0xaa1fada8,0x2f64ada8,0xaf648000,0x2a1fb000,0x2f648000,0xaa1f3000,0x2f64ada8,0x2a1f2da8,0xaf642da8,0xaa1fada8,0xaa1f3000,0xaf640000,0x2a1fb000,0x2f648000,
0xaf642a1f,0x2f64aa1f,0xaf642a1f,0x2f64aa1f,0xaa1f2f64,0x2a1faf64,0xaa1f2f64,0x2a1faf64,0x2a1faf64,0xaa1f2f64,0x2a1faf64,0xaa1f2f64,0xaf642a1f,0x2f64aa1f,0xaf642a1f,0x2f64aa1f,
0xada83000,0x2da8b000,0xada83000,0x2da8b000,0x2da88000,0xada80000,0x2da88000,0xada88000,0xada88000,0x2da88000,0xada80000,0x2da88000,0xada83000,0x2da8b000,0xada83000,0x2da8b000,
0xafd92ea7,0xa63e2c72,0x2fd9aea7,0x263eac72,0xac72263e,0xaea72fd9,0x2c72a63e,0x2ea7afd9,0x263eac72,0xafd92ea7,0xa63e2c72,0x2fd9aea7,0x2ea7afd9,0xac72263e,0xaea72fd9,0x2c72a63e,
0xaa1f2da8,0x2f64ada8,0x2a1fada8,0xaf642da8,0xaf643000,0x2a1f8000,0x2f64b000,0xaa1f8000,0xaf642da8,0xaa1f2da8,0x2f64ada8,0x2a1fada8,0xaa1f8000,0xaf643000,0x2a1f8000,0x2f64b000,
0x80008000,0x80000000,0x80000000,0x0,0x80000000,0x80000000,0x80000000,0x80000000,0xb0003000,0xb0003000,0xb0003000,0xb0003000,0xb0003000,0xb0003000,0xb0003000,0xb0003000,
0x3000b000,0x3000b000,0x3000b000,0x3000b000,0x3000b000,0x3000b000,0x3000b000,0x3000b000,0x80000000,0x80000000,0x80008000,0x80008000,0x80000000,0x80008000,0x80008000,0x80008000,
0x2f64ada8,0x2a1fada8,0xaf642da8,0xaa1f2da8,0x2a1f8000,0x2f64b000,0xaa1f8000,0xaf643000,0xaa1f2da8,0x2f64ada8,0x2a1fada8,0xaf642da8,0xaf643000,0x2a1f0000,0x2f64b000,0xaa1f8000,
0x263eac72,0xafd92ea7,0xa63e2c72,0x2fd9aea7,0x2ea7afd9,0xac72263e,0xaea72fd9,0x2c72a63e,0x2fd9aea7,0x263eac72,0xafd92ea7,0xa63e2c72,0x2c72a63e,0x2ea7afd9,0xac72263e,0xaea72fd9,
0xada83000,0x2da8b000,0xada83000,0x2da8b000,0x2da80000,0xada88000,0x2da88000,0xada88000,0x2da88000,0xada88000,0x2da80000,0xada88000,0x2da8b000,0xada83000,0x2da8b000,0xada83000,
0x2f64aa1f,0xaf642a1f,0x2f64aa1f,0xaf642a1f,0x2a1faf64,0xaa1f2f64,0x2a1faf64,0xaa1f2f64,0x2a1faf64,0xaa1f2f64,0x2a1faf64,0xaa1f2f64,0xaf642a1f,0x2f64aa1f,0xaf642a1f,0x2f64aa1f,
0x2f64ada8,0x2a1f2da8,0xaf642da8,0xaa1fada8,0xaa1f3000,0xaf648000,0x2a1fb000,0x2f640000,0xaa1fada8,0x2f64ada8,0x2a1f2da8,0xaf642da8,0x2f648000,0xaa1f3000,0xaf648000,0x2a1fb000,
0xaea7a63e,0x2c72afd9,0x2ea7263e,0xac722fd9,0x2fd9ac72,0x263e2ea7,0xafd92c72,0xa63eaea7,0xac722fd9,0xaea7a63e,0x2c72afd9,0x2ea7263e,0xa63eaea7,0x2fd9ac72,0x263e2ea7,0xafd92c72,
0xada8ada8,0xada8ada8,0xada8ada8,0xada8ada8,0x2da82da8,0x2da82da8,0x2da82da8,0x2da82da8,0x2da8ada8,0x2da8ada8,0x2da8ada8,0x2da8ada8,0xada82da8,0xada82da8,0xada82da8,0xada82da8,
0x30008000,0x30000000,0x30000000,0x30000000,0xb0008000,0xb0008000,0xb0008000,0xb0000000,0x80003000,0x80003000,0x80003000,0x3000,0xb000,0x8000b000,0xb000,0xb000,
0x2ea7a63e,0xac72afd9,0xaea7263e,0x2c722fd9,0xafd9ac72,0xa63e2ea7,0x2fd92c72,0x263eaea7,0x2c722fd9,0x2ea7a63e,0xac72afd9,0xaea7263e,0x263eaea7,0xafd9ac72,0xa63e2ea7,0x2fd92c72,
0xaa1f2da8,0x2f642da8,0x2a1fada8,0xaf64ada8,0x2f648000,0xaa1fb000,0xaf640000,0x2a1f3000,0xaf64ada8,0xaa1f2da8,0x2f642da8,0x2a1fada8,0x2a1f3000,0x2f648000,0xaa1fb000,0xaf648000,
0xaa1faf64,0x2a1f2f64,0xaa1faf64,0x2a1f2f64,0x2f642a1f,0xaf64aa1f,0x2f642a1f,0xaf64aa1f,0xaf64aa1f,0x2f642a1f,0xaf64aa1f,0x2f642a1f,0xaa1faf64,0x2a1f2f64,0xaa1faf64,0x2a1f2f64,
0x2da83000,0xada8b000,0x2da83000,0xada8b000,0xada88000,0x2da88000,0xada88000,0x2da80000,0x2da88000,0xada88000,0x2da80000,0xada80000,0x2da83000,0xada8b000,0x2da83000,0xada8b000,
0xa63eac72,0x2fd92ea7,0x263e2c72,0xafd9aea7,0xaea7afd9,0x2c72263e,0x2ea72fd9,0xac72a63e,0xafd9aea7,0xa63eac72,0x2fd92ea7,0x263e2c72,0xac72a63e,0xaea7afd9,0x2c72263e,0x2ea72fd9,
0x2a1f2da8,0xaf64ada8,0xaa1fada8,0x2f642da8,0x2f643000,0xaa1f8000,0xaf64b000,0x2a1f0000,0x2f642da8,0x2a1f2da8,0xaf64ada8,0xaa1fada8,0x2a1f8000,0x2f643000,0xaa1f8000,0xaf64b000,
0x3c003c00,0x3c003c00,0x3c003c00,0x3c003c00,0x3c003c00,0x3c003c00,0x3c003c00,0x3c003c00,0x80008000,0x80008000,0x80008000,0x80008000,0x80008000,0x80008000,0x80008000,0x80008000,
0x3bd93c00,0x3aa73b64,0x387239a8,0x323e361f,0xb23e0000,0xb872b61f,0xbaa7b9a8,0xbbd9bb64,0xb23e8000,0xb872b61f,0xbaa7b9a8,0xbbd9bb64,0xbbd9bc00,0xbaa7bb64,0xb872b9a8,0xb23eb61f,
0xbb64bc00,0xb61fb9a8,0x361f8000,0x3b6439a8,0x3b643c00,0x361f39a8,0xb61f0000,0xbb64b9a8,0x361f8000,0x3b6439a8,0x3b643c00,0x361f39a8,0xb61f8000,0xbb64b9a8,0xbb64bc00,0xb61fb9a8,
0x38728000,0x3bd93b64,0x323e39a8,0xbaa7b61f,0x3aa73c00,0xb23e361f,0xbbd9b9a8,0xb872bb64,0x3aa73c00,0xb23e361f,0xbbd9b9a8,0xb872bb64,0xb8728000,0xbbd9bb64,0xb23eb9a8,0x3aa7361f,
0xbc008000,0x3c008000,0xbc000000,0x3c008000,0xbc000000,0x3c008000,0xbc000000,0x3c008000,0x3c00,0x8000bc00,0x3c00,0x8000bc00,0x3c00,0x8000bc00,0x80003c00,0x8000bc00,
0xbbd98000,0x3aa7361f,0xb872b9a8,0x323e3b64,0x323ebc00,0xb8723b64,0x3aa7b9a8,0xbbd9361f,0xb23e3c00,0x3872bb64,0xbaa739a8,0x3bd9b61f,0xbbd90000,0x3aa7361f,0xb872b9a8,0x323e3b64,
0x3b648000,0xb61fb9a8,0xb61f3c00,0x3b64b9a8,0xbb648000,0x361f39a8,0x361fbc00,0xbb6439a8,0x361fbc00,0xbb6439a8,0x3b648000,0xb61fb9a8,0xb61f3c00,0x3b64b9a8,0xbb640000,0x361f39a8,
0xb8723c00,0x3bd9b61f,0xb23eb9a8,0xbaa73b64,0xbaa78000,0xb23e3b64,0x3bd9b9a8,0xb872b61f,0x3aa78000,0x323ebb64,0xbbd939a8,0x3872361f,0xb8723c00,0x3bd9b61f,0xb23eb9a8,0xbaa73b64,
0xbbd93c00,0xbaa73b64,0xb87239a8,0xb23e361f,0x323e8000,0x3872b61f,0x3aa7b9a8,0x3bd9bb64,0x323e8000,0x3872b61f,0x3aa7b9a8,0x3bd9bb64,0x3bd9bc00,0x3aa7bb64,0x3872b9a8,0x323eb61f,
0xbc003c00,0xbc003c00,0xbc003c00,0xbc003c00,0xbc003c00,0xbc003c00,0xbc003c00,0xbc003c00,0x80008000,0x80000000,0x80000000,0x80000000,0x80000000,0x80000000,0x0,0x80000000,
0xb8728000,0xbbd93b64,0xb23e39a8,0x3aa7b61f,0xbaa73c00,0x323e361f,0x3bd9b9a8,0x3872bb64,0xbaa73c00,0x323e361f,0x3bd9b9a8,0x3872bb64,0x38728000,0x3bd9bb64,0x323eb9a8,0xbaa7361f,
0x3b64bc00,0x361fb9a8,0xb61f8000,0xbb6439a8,0xbb643c00,0xb61f39a8,0x361f0000,0x3b64b9a8,0xb61f8000,0xbb6439a8,0xbb643c00,0xb61f39a8,0x361f8000,0x3b64b9a8,0x3b64bc00,0x361fb9a8,
0x3bd98000,0xbaa7361f,0x3872b9a8,0xb23e3b64,0xb23ebc00,0x38723b64,0xbaa7b9a8,0x3bd9361f,0x323e3c00,0xb872bb64,0x3aa739a8,0xbbd9b61f,0x3bd98000,0xbaa7361f,0x3872b9a8,0xb23e3b64,
0x3c008000,0xbc008000,0x3c000000,0xbc008000,0x3c000000,0xbc008000,0x3c000000,0xbc000000,0x80003c00,0xbc00,0x80003c00,0x8000bc00,0x80003c00,0xbc00,0x80003c00,0xbc00,
0x38723c00,0xbbd9b61f,0x323eb9a8,0x3aa73b64,0x3aa78000,0x323e3b64,0xbbd9b9a8,0x3872b61f,0xbaa78000,0xb23ebb64,0x3bd939a8,0xb872361f,0x38723c00,0xbbd9b61f,0x323eb9a8,0x3aa73b64,
0xbb640000,0x361fb9a8,0x361f3c00,0xbb64b9a8,0x3b648000,0xb61f39a8,0xb61fbc00,0x3b6439a8,0xb61fbc00,0x3b6439a8,0xbb640000,0x361fb9a8,0x361f3c00,0xbb64b9a8,0x3b648000,0xb61f39a8,
0x39a83c00,0xb9a80000,0xb9a8bc00,0x39a88000,0x39a83c00,0xb9a80000,0xb9a8bc00,0x39a88000,0xb9a88000,0xb9a8bc00,0x39a88000,0x39a83c00,0xb9a80000,0xb9a8bc00,0x39a88000,0x39a83c00,
0x38723c00,0xbbd9b61f,0x323eb9a8,0x3aa73b64,0xbaa70000,0xb23ebb64,0x3bd939a8,0xb872361f,0xbaa78000,0xb23ebb64,0x3bd939a8,0xb872361f,0xb872bc00,0x3bd9361f,0xb23e39a8,0xbaa7bb64,
0xb61fbc00,0x3b6439a8,0xbb640000,0x361fb9a8,0x361f3c00,0xbb64b9a8,0x3b648000,0xb61f39a8,0x3b648000,0xb61f39a8,0xb61fbc00,0x3b6439a8,0xbb648000,0x361fb9a8,0x361f3c00,0xbb64b9a8,
0x3bd98000,0xbaa7361f,0x3872b9a8,0xb23e3b64,0x323e3c00,0xb872bb64,0x3aa739a8,0xbbd9b61f,0x323e3c00,0xb872bb64,0x3aa739a8,0xbbd9b61f,0xbbd98000,0x3aa7b61f,0xb87239a8,0x323ebb64,
0xb9a88000,0xb9a83c00,0x39a88000,0x39a8bc00,0xb9a80000,0xb9a83c00,0x39a88000,0x39a8bc00,0xb9a83c00,0x39a88000,0x39a8bc00,0xb9a80000,0xb9a83c00,0x39a88000,0x39a8bc00,0xb9a88000,
0xb8728000,0xbbd93b64,0xb23e39a8,0x3aa7b61f,0x3aa7bc00,0xb23eb61f,0xbbd939a8,0xb8723b64,0xbaa73c00,0x323e361f,0x3bd9b9a8,0x3872bb64,0xb8728000,0xbbd93b64,0xb23e39a8,0x3aa7b61f,
0x361f8000,0x3b64b9a8,0x3b64bc00,0x361fb9a8,0xb61f8000,0xbb6439a8,0xbb643c00,0xb61f39a8,0x3b64bc00,0x361fb9a8,0xb61f8000,0xbb6439a8,0xbb643c00,0xb61f39a8,0x361f8000,0x3b64b9a8,
0xbbd93c00,0xbaa73b64,0xb87239a8,0xb23e361f,0xb23e8000,0xb872361f,0xbaa739a8,0xbbd93b64,0x323e8000,0x3872b61f,0x3aa7b9a8,0x3bd9bb64,0xbbd93c00,0xbaa73b64,0xb87239a8,0xb23e361f,
0xb8723c00,0x3bd9b61f,0xb23eb9a8,0xbaa73b64,0x3aa78000,0x323ebb64,0xbbd939a8,0x3872361f,0x3aa78000,0x323ebb64,0xbbd939a8,0x3872361f,0x3872bc00,0xbbd9361f,0x323e39a8,0x3aa7bb64,
0xb9a83c00,0x39a80000,0x39a8bc00,0xb9a88000,0xb9a83c00,0x39a88000,0x39a8bc00,0xb9a88000,0x39a88000,0x39a8bc00,0xb9a88000,0xb9a83c00,0x39a80000,0x39a8bc00,0xb9a88000,0xb9a83c00,
0xbbd98000,0x3aa7361f,0xb872b9a8,0x323e3b64,0xb23e3c00,0x3872bb64,0xbaa739a8,0x3bd9b61f,0xb23e3c00,0x3872bb64,0xbaa739a8,0x3bd9b61f,0x3bd98000,0xbaa7b61f,0x387239a8,0xb23ebb64,
0x361fbc00,0xbb6439a8,0x3b640000,0xb61fb9a8,0xb61f3c00,0x3b64b9a8,0xbb648000,0x361f39a8,0xbb648000,0x361f39a8,0x361fbc00,0xbb6439a8,0x3b648000,0xb61fb9a8,0xb61f3c00,0x3b64b9a8,
0x38728000,0x3bd93b64,0x323e39a8,0xbaa7b61f,0xbaa7bc00,0x323eb61f,0x3bd939a8,0x38723b64,0x3aa73c00,0xb23e361f,0xbbd9b9a8,0xb872bb64,0x38728000,0x3bd93b64,0x323e39a8,0xbaa7b61f,
0x39a88000,0x39a83c00,0xb9a88000,0xb9a8bc00,0x39a80000,0x39a83c00,0xb9a80000,0xb9a8bc00,0x39a83c00,0xb9a88000,0xb9a8bc00,0x39a88000,0x39a83c00,0xb9a88000,0xb9a8bc00,0x39a80000,
0x3bd93c00,0x3aa73b64,0x387239a8,0x323e361f,0x323e8000,0x3872361f,0x3aa739a8,0x3bd93b64,0xb23e8000,0xb872b61f,0xbaa7b9a8,0xbbd9bb64,0x3bd93c00,0x3aa73b64,0x387239a8,0x323e361f,
0xb61f8000,0xbb64b9a8,0xbb64bc00,0xb61fb9a8,0x361f8000,0x3b6439a8,0x3b643c00,0x361f39a8,0xbb64bc00,0xb61fb9a8,0x361f0000,0x3b6439a8,0x3b643c00,0x361f39a8,0xb61f8000,0xbb64b9a8,
0x0,0x0,0x0,0x0,0x0,0x0,0x0,0x0,0x3c003c00,0x3c003c00,0x3c003c00,0x3c003c00,0x3c003c00,0x3c003c00,0x3c003c00,0x3c003c00,
0x323e0000,0x3872361f,0x3aa739a8,0x3bd93b64,0x3bd93c00,0x3aa73b64,0x387239a8,0x323e361f,0x3bd93c00,0x3aa73b64,0x387239a8,0x323e361f,0xb23e0000,0xb872b61f,0xbaa7b9a8,0xbbd9bb64,
0xb61f0000,0xbb64b9a8,0xbb64bc00,0xb61fb9a8,0x361f0000,0x3b6439a8,0x3b643c00,0x361f39a8,0xbb64bc00,0xb61fb9a8,0x361f8000,0x3b6439a8,0x3b643c00,0x361f39a8,0xb61f0000,0xbb64b9a8,
0xbaa7bc00,0x323eb61f,0x3bd939a8,0x38723b64,0x38720000,0x3bd93b64,0x323e39a8,0xbaa7b61f,0x38728000,0x3bd93b64,0x323e39a8,0xbaa7b61f,0x3aa73c00,0xb23e361f,0xbbd9b9a8,0xb872bb64,
0x3c00,0x8000bc00,0x3c00,0x8000bc00,0x3c00,0x8000bc00,0x80003c00,0x8000bc00,0x3c000000,0xbc000000,0x3c008000,0xbc000000,0x3c008000,0xbc000000,0x3c008000,0xbc000000,
0xb23e3c00,0x3872bb64,0xbaa739a8,0x3bd9b61f,0xbbd90000,0x3aa7361f,0xb872b9a8,0x323e3b64,0x3bd90000,0xbaa7b61f,0x387239a8,0xb23ebb64,0xb23e3c00,0x3872bb64,0xbaa739a8,0x3bd9b61f,
0x361fbc00,0xbb6439a8,0x3b648000,0xb61fb9a8,0xb61f3c00,0x3b64b9a8,0xbb640000,0x361f39a8,0xbb640000,0x361f39a8,0x361fbc00,0xbb6439a8,0x3b640000,0xb61fb9a8,0xb61f3c00,0x3b64b9a8,
0x3aa78000,0x323ebb64,0xbbd939a8,0x3872361f,0xb8723c00,0x3bd9b61f,0xb23eb9a8,0xbaa73b64,0x3872bc00,0xbbd9361f,0x323e39a8,0x3aa7bb64,0x3aa70000,0x323ebb64,0xbbd939a8,0x3872361f,
0xb23e0000,0xb872361f,0xbaa739a8,0xbbd93b64,0xbbd93c00,0xbaa73b64,0xb87239a8,0xb23e361f,0xbbd93c00,0xbaa73b64,0xb87239a8,0xb23e361f,0x323e8000,0x3872b61f,0x3aa7b9a8,0x3bd9bb64,
0x0,0x8000,0x8000,0x8000,0x8000,0x8000,0x80008000,0x8000,0xbc003c00,0xbc003c00,0xbc003c00,0xbc003c00,0xbc003c00,0xbc003c00,0xbc003c00,0xbc003c00,
0x3aa7bc00,0xb23eb61f,0xbbd939a8,0xb8723b64,0xb8720000,0xbbd93b64,0xb23e39a8,0x3aa7b61f,0xb8728000,0xbbd93b64,0xb23e39a8,0x3aa7b61f,0xbaa73c00,0x323e361f,0x3bd9b9a8,0x3872bb64,
0x361f0000,0x3b64b9a8,0x3b64bc00,0x361fb9a8,0xb61f0000,0xbb6439a8,0xbb643c00,0xb61f39a8,0x3b64bc00,0x361fb9a8,0xb61f8000,0xbb6439a8,0xbb643c00,0xb61f39a8,0x361f0000,0x3b64b9a8,
0x323e3c00,0xb872bb64,0x3aa739a8,0xbbd9b61f,0x3bd98000,0xbaa7361f,0x3872b9a8,0xb23e3b64,0xbbd90000,0x3aa7b61f,0xb87239a8,0x323ebb64,0x323e3c00,0xb872bb64,0x3aa739a8,0xbbd9b61f,
0x80003c00,0xbc00,0x80003c00,0x8000bc00,0x80003c00,0xbc00,0x80003c00,0xbc00,0xbc000000,0x3c000000,0xbc008000,0x3c000000,0xbc008000,0x3c000000,0xbc008000,0x3c008000,
0xbaa78000,0xb23ebb64,0x3bd939a8,0xb872361f,0x38723c00,0xbbd9b61f,0x323eb9a8,0x3aa73b64,0xb872bc00,0x3bd9361f,0xb23e39a8,0xbaa7bb64,0xbaa70000,0xb23ebb64,0x3bd939a8,0xb872361f,
0xb61fbc00,0x3b6439a8,0xbb640000,0x361fb9a8,0x361f3c00,0xbb64b9a8,0x3b648000,0xb61f39a8,0x3b648000,0xb61f39a8,0xb61fbc00,0x3b6439a8,0xbb640000,0x361fb9a8,0x361f3c00,0xbb64b9a8,
0x39a80000,0x39a83c00,0xb9a80000,0xb9a8bc00,0x39a88000,0x39a83c00,0xb9a80000,0xb9a8bc00,0x39a83c00,0xb9a80000,0xb9a8bc00,0x39a88000,0x39a83c00,0xb9a80000,0xb9a8bc00,0x39a88000,
0x3aa70000,0x323e3b64,0xbbd9b9a8,0x3872b61f,0x38723c00,0xbbd9b61f,0x323eb9a8,0x3aa73b64,0x38723c00,0xbbd9b61f,0x323eb9a8,0x3aa73b64,0xbaa70000,0xb23ebb64,0x3bd939a8,0xb872361f,
0xbb640000,0x361fb9a8,0x361f3c00,0xbb64b9a8,0x3b640000,0xb61f39a8,0xb61fbc00,0x3b6439a8,0xb61fbc00,0x3b6439a8,0xbb640000,0x361fb9a8,0x361f3c00,0xbb64b9a8,0x3b648000,0xb61f39a8,
0xb23ebc00,0x38723b64,0xbaa7b9a8,0x3bd9361f,0x3bd90000,0xbaa7361f,0x3872b9a8,0xb23e3b64,0x3bd98000,0xbaa7361f,0x3872b9a8,0xb23e3b64,0x323e3c00,0xb872bb64,0x3aa739a8,0xbbd9b61f,
0xb9a83c00,0x39a88000,0x39a8bc00,0xb9a80000,0xb9a83c00,0x39a88000,0x39a8bc00,0xb9a88000,0x39a80000,0x39a8bc00,0xb9a80000,0xb9a83c00,0x39a88000,0x39a8bc00,0xb9a80000,0xb9a83c00,
0xbaa73c00,0x323e361f,0x3bd9b9a8,0x3872bb64,0xb8728000,0xbbd93b64,0xb23e39a8,0x3aa7b61f,0x38720000,0x3bd9bb64,0x323eb9a8,0xbaa7361f,0xbaa73c00,0x323e361f,0x3bd9b9a8,0x3872bb64,
0x3b64bc00,0x361fb9a8,0xb61f8000,0xbb6439a8,0xbb643c00,0xb61f39a8,0x361f8000,0x3b64b9a8,0xb61f0000,0xbb6439a8,0xbb643c00,0xb61f39a8,0x361f0000,0x3b64b9a8,0x3b64bc00,0x361fb9a8,
0x323e8000,0x3872b61f,0x3aa7b9a8,0x3bd9bb64,0xbbd93c00,0xbaa73b64,0xb87239a8,0xb23e361f,0x3bd9bc00,0x3aa7bb64,0x3872b9a8,0x323eb61f,0x323e0000,0x3872b61f,0x3aa7b9a8,0x3bd9bb64,
0xbaa70000,0xb23e3b64,0x3bd9b9a8,0xb872b61f,0xb8723c00,0x3bd9b61f,0xb23eb9a8,0xbaa73b64,0xb8723c00,0x3bd9b61f,0xb23eb9a8,0xbaa73b64,0x3aa78000,0x323ebb64,0xbbd939a8,0x3872361f,
0xb9a80000,0xb9a83c00,0x39a80000,0x39a8bc00,0xb9a88000,0xb9a83c00,0x39a80000,0x39a8bc00,0xb9a83c00,0x39a80000,0x39a8bc00,0xb9a88000,0xb9a83c00,0x39a88000,0x39a8bc00,0xb9a88000,
0x323ebc00,0xb8723b64,0x3aa7b9a8,0xbbd9361f,0xbbd90000,0x3aa7361f,0xb872b9a8,0x323e3b64,0xbbd98000,0x3aa7361f,0xb872b9a8,0x323e3b64,0xb23e3c00,0x3872bb64,0xbaa739a8,0x3bd9b61f,
0x3b640000,0xb61fb9a8,0xb61f3c00,0x3b64b9a8,0xbb640000,0x361f39a8,0x361fbc00,0xbb6439a8,0x361fbc00,0xbb6439a8,0x3b640000,0xb61fb9a8,0xb61f3c00,0x3b64b9a8,0xbb648000,0x361f39a8,
0x3aa73c00,0xb23e361f,0xbbd9b9a8,0xb872bb64,0x38728000,0x3bd93b64,0x323e39a8,0xbaa7b61f,0xb8720000,0xbbd9bb64,0xb23eb9a8,0x3aa7361f,0x3aa73c00,0xb23e361f,0xbbd9b9a8,0xb872bb64,
0x39a83c00,0xb9a88000,0xb9a8bc00,0x39a88000,0x39a83c00,0xb9a88000,0xb9a8bc00,0x39a80000,0xb9a80000,0xb9a8bc00,0x39a80000,0x39a83c00,0xb9a88000,0xb9a8bc00,0x39a88000,0x39a83c00,
0xb23e8000,0xb872b61f,0xbaa7b9a8,0xbbd9bb64,0x3bd93c00,0x3aa73b64,0x387239a8,0x323e361f,0xbbd9bc00,0xbaa7bb64,0xb872b9a8,0xb23eb61f,0xb23e0000,0xb872b61f,0xbaa7b9a8,0xbbd9bb64,
0xbb64bc00,0xb61fb9a8,0x361f0000,0x3b6439a8,0x3b643c00,0x361f39a8,0xb61f8000,0xbb64b9a8,0x361f0000,0x3b6439a8,0x3b643c00,0x361f39a8,0xb61f0000,0xbb64b9a8,0xbb64bc00,0xb61fb9a8,
};
__device__ __align__(1024) bf16 g_x1T[DM * XP];
__device__ __align__(1024) bf16 g_x2T[DM * XP];
__device__ __align__(1024) unsigned g_xcnt[10][4][32];
__device__ __align__(1024) uint4 g_of[8][16][1280];
__device__ __align__(1024) float g_fs[2][SEQ];

#define TS_SMEM 0
#define TS_DECL
#define TS_ARG
#define TS_PASS
#define TS_PHASE(p)
#define TS(i)
#define TSX(row, i)
#define TS_BEGIN
#define TS_END

struct cplx { float r, i; };
__device__ __forceinline__ cplx cmul(cplx a, cplx b) {
    cplx o;
    o.r = fmaf(a.r, b.r, -a.i * b.i);
    o.i = fmaf(a.r, b.i, a.i * b.r);
    return o;
}
__device__ __forceinline__ cplx csq(cplx a) {
    cplx o;
    o.r = fmaf(a.r, a.r, -a.i * a.i);
    o.i = 2.f * a.r * a.i;
    return o;
}
__device__ __forceinline__ cplx cexp_p(float arl, float ai, float p) {
    float mag = ex2(arl * p);
    float ang = ai * p;
    float n = rintf(ang * 0.15915494309189535f);
    float r = fmaf(n, -6.2831854820251465f, ang);
    r = fmaf(n, 1.7484555e-7f, r);
    cplx o;
    o.r = mag * __cosf(r);
    o.i = mag * __sinf(r);
    return o;
}

__device__ __forceinline__ uint32_t pack2h(float lo, float hi) {
    uint32_t r;
    asm("cvt.rn.f16x2.f32 %0, %1, %2;" : "=r"(r) : "f"(hi), "f"(lo));
    return r;
}
__device__ __forceinline__ uint32_t hmul(uint32_t a, uint32_t b) { uint32_t d; asm("mul.rn.f16x2 %0, %1, %2;" : "=r"(d) : "r"(a), "r"(b)); return d; }
__device__ __forceinline__ uint32_t hfma(uint32_t a, uint32_t b, uint32_t c) { uint32_t d; asm("fma.rn.f16x2 %0, %1, %2, %3;" : "=r"(d) : "r"(a), "r"(b), "r"(c)); return d; }
__device__ __forceinline__ uint32_t hfms(uint32_t a, uint32_t b, uint32_t c) {
    uint32_t d;
    asm("{\n.reg .b32 n;\nneg.f16x2 n, %1;\nfma.rn.f16x2 %0, n, %2, %3;\n}" : "=r"(d) : "r"(a), "r"(b), "r"(c));
    return d;
}
__device__ __forceinline__ uint32_t hadd(uint32_t a, uint32_t b) { uint32_t d; asm("add.rn.f16x2 %0, %1, %2;" : "=r"(d) : "r"(a), "r"(b)); return d; }
__device__ __forceinline__ uint32_t hsub(uint32_t a, uint32_t b) { uint32_t d; asm("sub.rn.f16x2 %0, %1, %2;" : "=r"(d) : "r"(a), "r"(b)); return d; }
__device__ __forceinline__ uint4 ldg_tab(int tab, int t) { return ldg128((const uint4*)c_fft + t + tab * 128); }
__device__ __forceinline__ uint32_t u4(const uint4& v, int i) { return i == 0 ? v.x : i == 1 ? v.y : i == 2 ? v.z : v.w; }
struct cpair { uint32_t r, i; };
__device__ __forceinline__ cpair pmul(cpair p, uint32_t z) {
    const __half2 zv = *reinterpret_cast<const __half2*>(&z), pr = *reinterpret_cast<const __half2*>(&p.r), pi = *reinterpret_cast<const __half2*>(&p.i);
    const __half2 zr = __low2half2(zv), zi = __high2half2(zv);
    const __half2 a = __hfma2(__hneg2(pi), zi, __hmul2(pr, zr)), b = __hfma2(pi, zr, __hmul2(pr, zi));
    return {*reinterpret_cast<const uint32_t*>(&a), *reinterpret_cast<const uint32_t*>(&b)};
}
__device__ __forceinline__ uint32_t packz(cplx z) { return pack2h(z.r, z.i); }
__device__ __forceinline__ void wgmma_kg(float (&d)[24], uint64_t da, uint64_t db, int scale_d) {
    asm volatile("{\n.reg .pred p;\nsetp.ne.b32 p, %26, 0;\n"
                 "wgmma.mma_async.sync.aligned.m64n48k16.f32.f16.f16 "
                 "{%0,%1,%2,%3,%4,%5,%6,%7,%8,%9,%10,%11,%12,%13,%14,%15,%16,%17,%18,%19,%20,%21,%22,%23}, %24, %25, p, 1, 1, 1, 1;\n}\n"
                 : "+f"(d[0]), "+f"(d[1]), "+f"(d[2]), "+f"(d[3]), "+f"(d[4]), "+f"(d[5]), "+f"(d[6]), "+f"(d[7]), "+f"(d[8]), "+f"(d[9]),
                   "+f"(d[10]), "+f"(d[11]), "+f"(d[12]), "+f"(d[13]), "+f"(d[14]), "+f"(d[15]), "+f"(d[16]), "+f"(d[17]), "+f"(d[18]), "+f"(d[19]),
                   "+f"(d[20]), "+f"(d[21]), "+f"(d[22]), "+f"(d[23])
                 : "l"(da), "l"(db), "r"(scale_d));
}

struct SsmParams { const bf16 *lar, *aim, *cre, *cim, *logdt, *dskip; const unsigned* epoch; };
constexpr int KG_TABLES = 6 * 16384, KG_RES = 1664;
struct KgShared { uint32_t kmax[6], kexp[6]; float cinv[6], tap0[6]; };
#define KS(f, i) (ks + (uint32_t)offsetof(KgShared, f) + 4 * (i))
struct KgParams { uint32_t l[3], a[3], r[3], i[3], dt, ds; };

__device__ __forceinline__ int cta_channel(int bx, int i) { return i < 2 ? 2 * bx + i : i < 4 ? 382 + 2 * bx + i : 256 + bx; }
__device__ __forceinline__ bool kg_is_hi(int warp) { return ((warp >> 1) ^ (warp >> 2)) & 1; }
__device__ __forceinline__ void kgen_load(KgParams& kp, int bx, int warp, int lane, const SsmParams& sp) {
    const int d = cta_channel(bx, 2 * (warp >> 2) + (warp & 1)), idx = d * (NMODE / 2) + lane;
    const bf16 *pr = kg_is_hi(warp) ? sp.cre : sp.lar, *pi = kg_is_hi(warp) ? sp.cim : sp.aim;
    kp.dt = __ldg((const uint16_t*)sp.logdt + d);
#pragma unroll
    for (int j = 0; j < 3; j++) {
        kp.l[j] = __ldg((const uint32_t*)sp.lar + idx + 32 * j); kp.a[j] = __ldg((const uint32_t*)sp.aim + idx + 32 * j);
        kp.r[j] = __ldg((const uint32_t*)pr + idx + 32 * j); kp.i[j] = __ldg((const uint32_t*)pi + idx + 32 * j);
    }
    kp.ds = __ldg((const uint16_t*)sp.dskip + cta_channel(bx, warp >> 1));
}

struct KgAnchors { uint32_t v[8]; };
__device__ __forceinline__ KgAnchors kg_anchor_lo(const KgParams& kp, uint32_t sel, float dt) {
    auto B = [&](uint32_t v) { return __uint_as_float(__byte_perm(v, 0u, sel)); };
    const float arl = -rbf(ex2(B(kp.l[0]) * 1.4426950408889634f)) * dt * 1.4426950408889634f, ai = B(kp.a[0]) * dt;
    const cplx z8 = cexp_p(arl, ai, 8.f), z16 = csq(z8), z24 = cmul(z16, z8), z32 = csq(z16), z64 = csq(z32), z128 = csq(z64), z192 = cmul(z128, z64);
    return {{pack2h(1.f, z8.r), pack2h(0.f, z8.i), pack2h(z16.r, z24.r), pack2h(z16.i, z24.i), packz(z32), packz(z64), packz(z128), packz(z192)}};
}
__device__ __forceinline__ KgAnchors kg_anchor_hi(const KgParams& kp, uint32_t sel, float dt, float cs) {
    auto B = [&](uint32_t v) { return __uint_as_float(__byte_perm(v, 0u, sel)); };
    const float arl = -rbf(ex2(B(kp.l[0]) * 1.4426950408889634f)) * dt * 1.4426950408889634f, ai = B(kp.a[0]) * dt;
    const cplx z1 = cexp_p(arl, -ai, 1.f), z2 = csq(z1), z4 = csq(z2), z256 = cexp_p(arl, -ai, 256.f), z512 = csq(z256), z1024 = csq(z512);
    const cplx H0 = {B(kp.r[0]) * cs, -B(kp.i[0]) * cs}, H4 = cmul(H0, z4);
    return {{pack2h(H0.r, H4.r), pack2h(H0.i, H4.i), packz(z1), packz(z2), packz(z256), packz(z512), packz(z1024), 0u}};
}

template <class Idle>
__device__ __forceinline__ void kgen_tables(KgParams& kp, uint32_t scr, uint32_t dump, uint32_t ks, int warp, int lane, Idle idle TS_ARG) {
    const int wg = warp >> 2, half = warp & 1, sw = lane & 7;
    const bool hi = kg_is_hi(warp);
    TS(23);
    const float dt = rbf(ex2(bf_lo(kp.dt) * 1.4426950408889634f));
    uint32_t sel = (wg == 2 && half) ? 0x3244u : 0x1044u;
    float cs = 0.f;
    KgAnchors an;
    if (hi) {
        uint32_t m = 0;
#pragma unroll
        for (int j = 0; j < 3; j++) m = __vmaxu2(m, __vmaxu2(kp.r[j] & 0x7FFF7FFFu, kp.i[j] & 0x7FFF7FFFu));
        m = __reduce_max_sync(~0u, max(m << 16, m & 0xFFFF0000u));
        const uint32_t e = min(max(__float_as_uint(2.f * dt * __uint_as_float(m)) >> 23, 2u), 252u);
        cs = 2.f * dt * __uint_as_float((253u - e) << 23);
        if (lane == 0) { sts32(KS(cinv, 2 * wg + half), (e + 1u) << 23); sts32(KS(kmax, 2 * wg + half), 0u); }
        an = kg_anchor_hi(kp, sel, dt, cs);
    } else {
        an = kg_anchor_lo(kp, sel, dt);
    }
    float acc[24];
#pragma unroll
    for (int i = 0; i < 24; i++) acc[i] = 0.f;
    uint32_t tb = scr + 2 * wg * 16384 + lane * 128;
    uint64_t da = mkdesc(scr + 2 * wg * 16384, 4096, 1024, 1);
    int flip = 16384;
#pragma unroll 1
    for (int c = wg == 2 ? 1 : 0, step = wg == 2 ? 2 : 1; c < 6; c += step) {
        if (wg < 2) sel ^= 0x2200u;
        if (!hi) {
            if (c & 1) { kp.l[0] = kp.l[1]; kp.l[1] = kp.l[2]; kp.a[0] = kp.a[1]; kp.a[1] = kp.a[2]; }
            cpair p[4];
            p[0] = {an.v[0], an.v[1]}; p[1] = {an.v[2], an.v[3]};
            p[2] = pmul(p[0], an.v[4]); p[3] = pmul(p[1], an.v[4]);
#pragma unroll
            for (int j = 0; j < 4; j++) {
                cpair v[4];
#pragma unroll
                for (int i = 0; i < 4; i++) v[i] = j ? pmul(p[i], an.v[4 + j]) : p[i];
                const uint32_t a = tb + (((4 * half + j) ^ sw) << 4);
                sts128(a, make_uint4(v[0].r, v[1].r, v[2].r, v[3].r));
                sts128(a + 4096, make_uint4(v[0].i, v[1].i, v[2].i, v[3].i));
            }
            an = kg_anchor_lo(kp, sel, dt);
        } else {
            if (c & 1) {
#pragma unroll
                for (int j = 0; j < 2; j++) { kp.l[j] = kp.l[j + 1]; kp.a[j] = kp.a[j + 1]; kp.r[j] = kp.r[j + 1]; kp.i[j] = kp.i[j + 1]; }
            }
            const uint32_t h1 = an.v[2], h2 = an.v[3], h256 = an.v[4], h512 = an.v[5], h1024 = an.v[6];
            cpair p[11];
            p[0] = {an.v[0], an.v[1]};
            p[1] = pmul(p[0], h2); p[2] = pmul(p[0], h1); p[3] = pmul(p[1], h1);
            p[4] = pmul(p[0], h256); p[5] = pmul(p[1], h256); p[6] = pmul(p[0], h512); p[7] = pmul(p[4], h512);
            p[8] = pmul({__byte_perm(p[0].r, p[4].r, 0x5410), __byte_perm(p[0].i, p[4].i, 0x5410)}, h1024);
            p[9] = pmul(p[8], h512); p[10] = pmul(p[8], h1024);
#pragma unroll
            for (int j = 0; j < 3; j++) {
                const uint32_t a = tb + 8192 + (((3 * half + j) ^ sw) << 4);
                sts128(a, make_uint4(p[4 * j].r, p[4 * j + 1].r, p[4 * j + 2].r, p[j < 2 ? 4 * j + 3 : 10].r));
                sts128(a + 4096, make_uint4(p[4 * j].i, p[4 * j + 1].i, p[4 * j + 2].i, p[j < 2 ? 4 * j + 3 : 10].i));
            }
            an = kg_anchor_hi(kp, sel, dt, cs);
        }
        if (c == 0) TS(24);
        if (c == 3) TS(25);
        fence_async_smem();
        wg_wait<0>();
        named_bar(5 + wg, 128);
        wg_fence();
#pragma unroll
        for (int k = 0; k < 4; k++) wgmma_kg(acc, da + k * 128, da + 512 + k * 128, 1);
        wg_commit();
        tb += flip; da += flip >> 4; flip = -flip;
    }
    const bool up = warp & 2;
    const int r = 2 * wg + up, lo0 = 16 * half + (lane >> 2);
    const uint32_t o = dump + r * KG_RES + lo0 * 52 + 4 * (lane & 3);
    const float ci = __uint_as_float(lds32(KS(cinv, r)));
    const float ds = warp <= 8 ? bf_lo(kp.ds) : 0.f;
    TS(26);
    idle();
    wg_wait<0>();
    float v[12], m = 0.f;
#pragma unroll
    for (int j = 0; j < 12; j++) { v[j] = up ? acc[12 + j] : acc[j]; m = fmaxf(m, fabsf(v[j])); }
#pragma unroll
    for (int j = 0; j < 6; j++) sts32(o + (j & 1) * 416 + (j >> 1) * 16, pack2h(v[2 * j], v[2 * j + 1]));
    const uint32_t mm = __reduce_max_sync(~0u, __float_as_uint(m));
    if (lane == 0) {
        asm volatile("red.shared.max.u32 [%0], %1;" ::"r"(KS(kmax, r)), "r"(mm) : "memory");
        if (!half) sts32(KS(tap0, r), __float_as_uint(fmaf(ci, v[0], ds)));
    }
}
#define F_STAG 4
__device__ __forceinline__ void wgmma_h64_rs(uint32_t (&d)[16], const uint4& a, uint64_t db, int scale_d) {
    asm volatile("{\n.reg .pred p;\nsetp.ne.b32 p, %21, 0;\n"
                 "wgmma.mma_async.sync.aligned.m64n64k16.f16.f16.f16 {%0,%1,%2,%3,%4,%5,%6,%7,%8,%9,%10,%11,%12,%13,%14,%15}, {%16,%17,%18,%19}, %20, p, 1, 1, 1;\n}\n"
                 : "+r"(d[0]), "+r"(d[1]), "+r"(d[2]), "+r"(d[3]), "+r"(d[4]), "+r"(d[5]), "+r"(d[6]), "+r"(d[7]), "+r"(d[8]), "+r"(d[9]),
                   "+r"(d[10]), "+r"(d[11]), "+r"(d[12]), "+r"(d[13]), "+r"(d[14]), "+r"(d[15])
                 : "r"(a.x), "r"(a.y), "r"(a.z), "r"(a.w), "l"(db), "r"(scale_d));
}
template <int TB>
__device__ __forceinline__ void wgmma_h32_rs(uint32_t (&d)[8], const uint4& a, uint64_t db, int scale_d) {
    asm volatile("{\n.reg .pred p;\nsetp.ne.b32 p, %13, 0;\n"
                 "wgmma.mma_async.sync.aligned.m64n32k16.f16.f16.f16 {%0,%1,%2,%3,%4,%5,%6,%7}, {%8,%9,%10,%11}, %12, p, 1, 1, %14;\n}\n"
                 : "+r"(d[0]), "+r"(d[1]), "+r"(d[2]), "+r"(d[3]), "+r"(d[4]), "+r"(d[5]), "+r"(d[6]), "+r"(d[7])
                 : "r"(a.x), "r"(a.y), "r"(a.z), "r"(a.w), "l"(db), "r"(scale_d), "n"(TB));
}
__device__ __forceinline__ void wgmma_s1(uint32_t (&d)[16], const uint4& a, uint64_t db, int scale_d) { wgmma_h64_rs(d, a, db, scale_d); }
__device__ __forceinline__ void wgmma_s1(uint32_t (&d)[8], const uint4& a, uint64_t db, int scale_d) { wgmma_h32_rs<1>(d, a, db, scale_d); }
__device__ __forceinline__ void wgmma_s4(float (&d)[32], const uint4& a, uint64_t db, uint32_t meta, int scale_d) {
    asm volatile("{\n.reg .pred p;\nsetp.ne.b32 p, %38, 0;\n"
                 "wgmma.mma_async.sp.sync.aligned.m64n64k32.f32.f16.f16 {%0,%1,%2,%3,%4,%5,%6,%7,%8,%9,%10,%11,%12,%13,%14,%15,%16,%17,%18,%19,%20,%21,%22,%23,%24,%25,%26,%27,%28,%29,%30,%31}, {%32,%33,%34,%35}, %36, %37, 0, p, 1, 1, 1;\n}\n"
                 : "+f"(d[0]), "+f"(d[1]), "+f"(d[2]), "+f"(d[3]), "+f"(d[4]), "+f"(d[5]), "+f"(d[6]), "+f"(d[7]), "+f"(d[8]), "+f"(d[9]), "+f"(d[10]), "+f"(d[11]), "+f"(d[12]), "+f"(d[13]), "+f"(d[14]), "+f"(d[15]), "+f"(d[16]), "+f"(d[17]), "+f"(d[18]), "+f"(d[19]), "+f"(d[20]), "+f"(d[21]), "+f"(d[22]), "+f"(d[23]), "+f"(d[24]), "+f"(d[25]), "+f"(d[26]), "+f"(d[27]), "+f"(d[28]), "+f"(d[29]), "+f"(d[30]), "+f"(d[31])
                 : "r"(a.x), "r"(a.y), "r"(a.z), "r"(a.w), "l"(db), "r"(meta), "r"(scale_d));
}
__device__ __forceinline__ void wgmma_s4(float (&d)[16], const uint4& a, uint64_t db, uint32_t meta, int scale_d) {
    asm volatile("{\n.reg .pred p;\nsetp.ne.b32 p, %22, 0;\n"
                 "wgmma.mma_async.sp.sync.aligned.m64n32k32.f32.f16.f16 {%0,%1,%2,%3,%4,%5,%6,%7,%8,%9,%10,%11,%12,%13,%14,%15}, {%16,%17,%18,%19}, %20, %21, 0, p, 1, 1, 1;\n}\n"
                 : "+f"(d[0]), "+f"(d[1]), "+f"(d[2]), "+f"(d[3]), "+f"(d[4]), "+f"(d[5]), "+f"(d[6]), "+f"(d[7]), "+f"(d[8]), "+f"(d[9]), "+f"(d[10]), "+f"(d[11]), "+f"(d[12]), "+f"(d[13]), "+f"(d[14]), "+f"(d[15])
                 : "r"(a.x), "r"(a.y), "r"(a.z), "r"(a.w), "l"(db), "r"(meta), "r"(scale_d));
}

__device__ __forceinline__ uint32_t& u4r(uint4& v, int i) { return i == 0 ? v.x : i == 1 ? v.y : i == 2 ? v.z : v.w; }

template <int NC>
__device__ __forceinline__ void fft_stage(const uint32_t (&u)[2][4], int c, uint32_t eo, int w, int lane) {
    const int mi = lane >> 3, mj = lane & 7;
    const uint32_t a = eo + (8 * w + mj) * 128 + (((4 * c + mi) ^ mj) << 4);
    stsm_x4(a, hadd(u[0][0], u[1][0]), hadd(u[0][1], u[1][1]), hadd(u[0][2], u[1][2]), hadd(u[0][3], u[1][3]));
    stsm_x4(NC == 2 ? a + 4096 : a ^ 64, hsub(u[0][0], u[1][0]), hsub(u[0][1], u[1][1]), hsub(u[0][2], u[1][2]), hsub(u[0][3], u[1][3]));
}
template <int NC>
__device__ __forceinline__ void kernel_stage(const uint4 (&ko)[2], uint32_t kt, uint32_t ks, int r, uint32_t eo, int w, int lane) {
    uint32_t u[2][2][4], sc[NC], t0[NC];
#pragma unroll
    for (int c = 0; c < NC; c++) {
        auto L = [](uint32_t a) { return __uint_as_float(lds32(a)); };
        const float ci = L(KS(cinv, r + c)), k0 = L(KS(tap0, r + c)) + (NC == 1 ? L(KS(tap0, r + 1)) : 0.f);
        const float mx = fmaxf(ci * (L(KS(kmax, r + c)) + (NC == 1 ? L(KS(kmax, r + 1)) : 0.f) + 0x1p-14f), fabsf(k0));
        const uint32_t e = min(max(__float_as_uint(mx) >> 23, 4u), 250u);
        const float s = __uint_as_float((253u - e) << 23), f = s * ci;
        if (w == 0 && lane == 0) sts32(KS(kexp, r + c), e);
        sc[c] = pack2h(f, f); t0[c] = pack2h(k0 * s, 0.f);
    }
#pragma unroll
    for (int h = 0; h < 2; h++)
#pragma unroll
        for (int j = 0; j < 4; j++) {
            const uint32_t a0 = kt + (u4(ko[h], j) & 0xFFFF), a1 = kt + (u4(ko[h], j) >> 16);
#pragma unroll
            for (int c = 0; c < 2; c++)
                asm volatile("{\n.reg .b16 a, b;\nld.shared.b16 a, [%1];\nld.shared.b16 b, [%2];\nmov.b32 %0, {a, b};\n}"
                             : "=r"(u[c][h][j]) : "r"(a0 + c * KG_RES), "r"(a1 + c * KG_RES) : "memory");
            if (NC == 1) u[0][h][j] = hadd(u[0][h][j], u[1][h][j]);
#pragma unroll
            for (int c = 0; c < NC; c++) {
                u[c][h][j] = hmul(u[c][h][j], sc[c]);
                if (h + j == 0 && w == 0 && lane == 0) u[c][0][0] = __byte_perm(t0[c], u[c][0][0], 0x7610);
            }
        }
#pragma unroll
    for (int c = 0; c < NC; c++) fft_stage<NC>(u[c], c, eo, w, lane);
}

template <int NC, bool SHEAR, class Mid>
__device__ __forceinline__ void fft_forward(const uint4 (&a1)[4], const uint4 (&tw)[4], uint32_t eo, uint32_t s2, uint32_t (&X)[NC][2][8], Mid mid) {
    uint32_t dr[8 * NC], di[8 * NC];
    const uint64_t de = mkdesc(eo, 4096, 1024, 1), d2 = mkdesc(s2, 16, 1024, 1);
    wg_fence();
    wgmma_s1(dr, a1[0], de, 0);
    wgmma_s1(di, a1[2], de + (NC == 2 ? 256 : 4), 0);
    wgmma_s1(dr, a1[1], de + 128, 1);
    wgmma_s1(di, a1[3], de + (NC == 2 ? 384 : 132), 1);
    wg_commit();
    mid();
    wg_wait<0>();
#pragma unroll
    for (int c = 0; c < NC; c++) {
        uint4 zr[2], zi[2];
#pragma unroll
        for (int p = 0; p < 2; p++)
#pragma unroll
            for (int i = 0; i < 4; i++) {
                const uint32_t r = dr[8 * c + 4 * p + i], m = di[8 * c + 4 * p + i], tr = u4(tw[p], i), ti = u4(tw[2 + p], i);
                if (SHEAR) {
                    const uint32_t r1 = hfma(tr, m, r), m1 = hfma(ti, r1, m);
                    u4r(zr[p], i) = hfma(tr, m1, r1); u4r(zi[p], i) = m1;
                } else {
                    u4r(zr[p], i) = hfms(m, ti, hmul(r, tr));
                    u4r(zi[p], i) = hfma(m, tr, hmul(r, ti));
                }
            }
        wg_fence();
        wgmma_h32_rs<0>(X[c][0], zi[0], d2 + 2, 0);
        wgmma_h32_rs<0>(X[c][1], zi[1], d2 + 6, 0);
        wgmma_h32_rs<0>(X[c][0], zr[0], d2, 1);
        wgmma_h32_rs<0>(X[c][1], zr[1], d2 + 4, 1);
        wg_commit();
    }
}

template <int NC, class Idle, class Staged>
__device__ __forceinline__ void conv_wg(int ch0, int layer, uint32_t eo, uint32_t zb, uint32_t s23, uint32_t kexp, uint32_t epoch, uint32_t st, uint32_t sbar, uint32_t rbar, uint32_t fbar,
                                        int warp, int lane, uint4 (&a1)[4], uint4 (&tw)[4], Idle idle, Staged staged TS_ARG) {
    const int wg = warp >> 2, w = warp & 3, t = 32 * w + lane, q = lane & 3, mi = lane >> 3, mj = lane & 7;
    auto F = [](uint32_t x) { return __uint_as_float(x); };
    uint32_t KH[NC][2][8];
    TS(2);
    fft_forward<NC, false>(a1, tw, eo, s23, KH, [] {});
    named_bar(1 + wg, 128);
    uint4 a4[4];
#pragma unroll
    for (int i = 0; i < 4; i++) if (NC == 2) { tw[i] = ldg_tab(4 + i, t); a4[i] = ldg_tab(12 + i, t); }
    wg_wait<0>();
    TS(4);
    idle();
    uint2 x[NC][2][2];
    const uint32_t ra[2] = {4u * t, 4u * (t ^ 252)};
    if (w == 0) {
        const bf16* pp = g_x1T + (uint32_t)(ch0 + NC - 1) * XP + 64 * lane + 60;
        uint32_t v;
        int spin = 0;
        do { asm volatile("ld.relaxed.gpu.global.u32 %0, [%1];" : "=r"(v) : "l"(pp) : "memory"); } while (__any_sync(~0u, ~(v ^ layer) & 1u) && ++spin < (1 << 18));
        if (lane == 0) mbar_arrive(rbar);
    } else {
        mbar_wait(rbar, 0);
    }
    TS(5);
    auto xload = [&](int i) {
        const unsigned long long v = ld_ll((const unsigned long long*)(g_x1T + (uint32_t)ch0 * XP + ra[(i >> 1) & 1] + ((i >> 2) * XP + 1024 * (i & 1))));
        x[i >> 2][(i >> 1) & 1][i & 1] = make_uint2((uint32_t)v, (uint32_t)(v >> 32));
    };
#pragma unroll
    for (int i = 0; i < 4 * NC; i++) xload(i);
    TS(6);
    if (NC == 1) {
        uint4 s[8];
        TS(1);
#pragma unroll
        for (int i = 0; i < 8; i++) s[i] = make_uint4(layer, 0, 0, 0);
        int spin = 0;
        uint32_t bad;
        do {
            bad = 0;
#pragma unroll
            for (int i = 0; i < 8; i++)
                if (((s[i].x ^ layer) & 1u) == 0) s[i] = ld_ll4((const uint4*)(g_fs[0] + ra[i >> 2] + (SEQ * (i & 1) + 1024 * ((i >> 1) & 1))));
#pragma unroll
            for (int i = 0; i < 8; i++) bad |= ~(s[i].x ^ layer);
        } while ((bad & 1u) && ++spin < (1 << 18));
#pragma unroll
        for (int i = 0; i < 8; i++) sts128(st + i * 2048 + t * 16, s[i]);
        __syncwarp();
        if (lane == 0) mbar_arrive(sbar + 8 * w);
        TS(14);
    }
    for (int spin = 0; spin < (1 << 18); spin++) {
        uint32_t bad = 0;
#pragma unroll
        for (int i = 0; i < 4 * NC; i++) bad |= ~(x[i >> 2][(i >> 1) & 1][i & 1].x ^ layer);
        if (!(bad & 1u)) break;
#pragma unroll
        for (int i = 0; i < 4 * NC; i++) if (((x[i >> 2][(i >> 1) & 1][i & 1].x ^ layer) & 1u) == 0) xload(i);
    }
    __syncwarp();
#pragma unroll
    for (int i = 0; i < 4; i++) if (NC == 1) { tw[i] = ldg_tab(4 + i, t); a4[i] = ldg_tab(12 + i, t); }
    TS(26);
    if (NC == 2) mbar_wait(sbar + 8 * w, 0);
    staged();
    {
        uint4 s[2][2][2];
        uint32_t u[NC][2][4];
#pragma unroll
        for (int h = 0; h < 2; h++) {
            if (NC == 1 || h == 0) {
#pragma unroll
                for (int i = 4 * h; i < (NC == 1 ? 4 * h + 4 : 8); i++) s[i >> 2][(i >> 1) & 1][i & 1] = lds128(st + i * 2048 + t * 16);
            }
            if (h == 0) TS(7);
#pragma unroll
            for (int c = 0; c < NC; c++)
#pragma unroll
                for (int j = 0; j < 4; j++) {
                    const uint4 &a = s[h][j >> 1][0], &b = s[h][j >> 1][1];
                    const uint32_t xv = (j & 1) ? x[c][h][j >> 1].y : x[c][h][j >> 1].x;
                    u[c][h][j] = pack2h(fmaf(bf_lo(xv), F(u4(a, 2 * (j & 1))), F(u4(b, 2 * (j & 1)))), fmaf(bf_hi(xv), F(u4(a, 2 * (j & 1) + 1)), F(u4(b, 2 * (j & 1) + 1))));
                }
        }
#pragma unroll
        for (int c = 0; c < NC; c++) fft_stage<NC>(u[c], c, eo, w, lane);
    }
    TS(8);
    fence_async_smem();
    TS(9);
    named_bar(1 + wg, 128);
    uint32_t X[NC][2][8], Y[NC][2][8];
    uint32_t oscale[NC];
    fft_forward<NC, true>(a1, tw, eo, s23, X, [&] {
#pragma unroll
        for (int c = 0; c < NC; c++) oscale[c] = (lds32(kexp + 4 * c) + 3u) * 0x00800080u;
        if (layer) {
#pragma unroll
            for (int i = 0; i < 4 * NC; i++) asm volatile("mov.b32 %0, 0;\nmov.b32 %1, 0;" : "=r"(x[i >> 2][(i >> 1) & 1][i & 1].x), "=r"(x[i >> 2][(i >> 1) & 1][i & 1].y));
        }
        if (NC == 2 && wg == 1 && lane == 0) mbar_arrive(fbar);
        TS(3); if (F_STAG >= 2 && NC == 2 && wg == 1) named_bar(10 + w, 64); });
    if (F_STAG == 2 && NC == 2 && wg == 0) asm volatile("bar.arrive %0, 64;" ::"r"(10 + w) : "memory");
    TS(10);
    const uint64_t d3 = mkdesc(s23 + 4096, 16, 1024, 1);
#pragma unroll
    for (int c = 0; c < NC; c++) {
        wg_wait<NC - 1>();
        TS(11 + c);
        uint4 pr[2], pi[2];
#pragma unroll
        for (int i = 0; i < 4; i++) {
            const uint32_t er = X[c][0][i], ei = X[c][0][4 + i], orr = X[c][1][i], oi = X[c][1][4 + i];
            const uint32_t ar = KH[c][0][i], ai = KH[c][0][4 + i], br = KH[c][1][i], bi = KH[c][1][4 + i];
            u4r(pr[0], i) = hfms(bi, oi, hfma(br, orr, hfms(ai, ei, hmul(ar, er))));
            u4r(pi[0], i) = hfma(bi, orr, hfma(br, oi, hfma(ai, er, hmul(ar, ei))));
            u4r(pr[1], i) = hfms(ai, oi, hfma(ar, orr, hfms(bi, ei, hmul(br, er))));
            u4r(pi[1], i) = hfma(ai, orr, hfma(ar, oi, hfma(bi, er, hmul(br, ei))));
        }
        if (F_STAG == 3 + c && NC == 2 && wg == 0) asm volatile("bar.arrive %0, 64;" ::"r"(10 + w), "r"(pr[0].x ^ pr[1].w ^ pi[0].y ^ pi[1].z) : "memory");
        wg_fence();
        wgmma_h32_rs<0>(Y[c][0], pr[0], d3, 0);
        wgmma_h32_rs<0>(Y[c][1], pr[1], d3 + 4, 0);
        wgmma_h32_rs<0>(Y[c][0], pi[0], d3 + 2, 1);
        wgmma_h32_rs<0>(Y[c][1], pi[1], d3 + 6, 1);
        wg_commit();
    }
#pragma unroll
    for (int c = 0; c < NC; c++) {
        if (c + 1 < NC) wg_wait<1>(); else wg_wait<0>();
        TS(13 + c);
        uint32_t zr[2][4], zi[2][4];
#pragma unroll
        for (int p = 0; p < 2; p++)
#pragma unroll
            for (int i = 0; i < 4; i++) {
                const uint32_t r = Y[c][p][i], m = Y[c][p][4 + i], tr = u4(tw[p], i), ti = u4(tw[2 + p], i);
                const uint32_t r1 = hfms(tr, m, r), m1 = hfms(ti, r1, m);
                zr[i & 1][2 * p + (i >> 1)] = hfms(tr, m1, r1);
                zi[i & 1][2 * p + (i >> 1)] = m1;
            }
        const int kr = 4 * (mj >> 1) + (mj & 1) + 2 * (mj >> 2), ki = kr ^ 2;
#pragma unroll
        for (int h = 0; h < 2; h++) {
            const uint32_t a = zb + (2 * w + h) * 2048;
            stsm_x4(a + ki * 128 + (((4 * c + mi) ^ (ki & 7)) << 4), zi[h][0], zi[h][1], zi[h][2], zi[h][3]);
            stsm_x4(a + kr * 128 + (((4 * c + mi) ^ (kr & 7)) << 4), zr[h][0], zr[h][1], zr[h][2], zr[h][3]);
        }
    }
    TS(15);
    fence_async_smem();
    TS(16);
    named_bar(1 + wg, 128);
    TS(17);
    float acc[16 * NC];
    const uint64_t dz = mkdesc(zb, 4096, 1024, 1);
    wg_fence();
#pragma unroll
    for (int ks = 0; ks < 4; ks++) wgmma_s4(acc, a4[ks], dz + ks * 256, 0x44EEEE44u, ks > 0);
    wg_commit();
    const uint32_t fb = ~lds32(epoch);
    uint32_t mk[NC][3];
#pragma unroll
    for (int c = 0; c < NC; c++) {
        const int k = ((ch0 + c) >> 1) & 3;
        mk[c][2] = !layer && k == 2 * q; mk[c][1] = !layer && k == 2 * q + 1; mk[c][0] = mk[c][2] | layer;
    }
    auto mark = [&](uint32_t v, uint32_t m) { return (v & ~m) | (fb & m); };
    const char* dst[2];
    {
        uint32_t l2;
        asm volatile("mov.u32 %0, %%laneid;" : "=r"(l2));
        const char* base = layer ? (const char*)g_of + (uint32_t)(ch0 / 80) * 327680u + (uint32_t)(ch0 % 80) * 256u : (const char*)g_x2T + (uint32_t)ch0 * (XP * 2u);
#pragma unroll
        for (int h = 0; h < 2; h++) {
            const uint32_t v = (32 * w + l2) ^ (h ? 252u : 0u);
            dst[h] = base + (layer ? (v >> 4) * 20480u + (v & 15u) * 16u : v * 8u);
        }
    }
    wg_wait<0>();
    TS(18);
#pragma unroll
    for (int c = 0; c < NC; c++) {
        uint32_t r[2][4];
#pragma unroll
        for (int j = 0; j < 4; j++) {
            const float* d = acc + 4 * (4 * c + j);
            const uint32_t y0 = pack2(d[0] + d[2], d[1] + d[3]), y1 = pack2(d[0] - d[2], d[1] - d[3]);
            asm("fma.rn.bf16x2 %0, %1, %2, %3;" : "=r"(r[0][j]) : "r"(y0), "r"(oscale[c]), "r"((j & 1) ? x[c][0][j >> 1].y : x[c][0][j >> 1].x));
            asm("fma.rn.bf16x2 %0, %1, %2, %3;" : "=r"(r[1][j]) : "r"(y1), "r"(oscale[c]), "r"((j & 1) ? x[c][1][j >> 1].y : x[c][1][j >> 1].x));
        }
#pragma unroll
        for (int h = 0; h < 2; h++)
            asm volatile("{\n.reg .pred p;\n.reg .b128 t;\n.reg .b64 a, b;\nsetp.ne.u32 p, %5, 0;\nmov.b64 a, {%1, %2};\nmov.b64 b, {%3, %4};\nmov.b128 t, {a, b};\n"
                         "@p st.relaxed.gpu.global.b128 [%0], t;\n@!p st.relaxed.gpu.global.b64 [%6], a;\n@!p st.relaxed.gpu.global.b64 [%6 + 2048], b;\n}"
                         ::"l"(dst[h] + c * 256), "r"(mark(r[h][0], mk[c][0])), "r"(mark(r[h][1], mk[c][1])), "r"(mark(r[h][2], mk[c][2])), "r"(mark(r[h][3], mk[c][1])), "r"(layer), "l"(dst[h] + c * XP * 2) : "memory");
    }
    if (layer == 0 && lane == 0) asm volatile("red.relaxed.gpu.global.add.u32 [%0], %1;" ::"l"(g_xcnt[ch0 >> 6][w]), "n"(NC) : "memory");
    TS(19);
}

#define Q_S0 8
#define R_CONS 192
#define K_CSUN 1
constexpr int K_CSU = K_CSUN;
#define G_MAP 1
constexpr int Q_SP = 4;
#define A_VLO 4
#define X_ARR 0
#define X_DELAY 0
constexpr int Q_ST = 4;
constexpr int Q_AB = 16384, Q_BB = 30720, Q_SB = Q_AB + Q_BB;
constexpr int Q_EROW = 336;
constexpr int Q_ESLOT = 8 * Q_EROW;
constexpr int Q_EOFF = Q_ST * Q_SB;
constexpr int Q_KG = 2 * Q_SB;
static_assert(3 * Q_ESLOT <= 8192 && Q_KG + KG_TABLES <= Q_EOFF + 4096, "exchange slots, kernel generation");
constexpr int F_EO = Q_EOFF, F_S23 = F_EO + 2 * 8192 + 4096, Q_KDUMP = F_S23 + 8192;
constexpr int Q_MISC = Q_KDUMP + 6 * KG_RES;
__host__ __device__ constexpr int w_grp(int j) { return j < 7 ? 2 * Q_SB + 4096 + j * 12800 : 0; }
constexpr int W_RES = Q_AB;
__device__ __forceinline__ int o_slot(int wg, int s) { return W_RES + (((2 * s + 2) & 7) + wg) * 10240; }
__device__ __forceinline__ int w_out(int wg) { return W_RES + (2 + 3 * wg) * 10240; }
static_assert(W_RES + 8 * 10240 == w_grp(0) && w_grp(6) + 12800 <= Q_EOFF && w_grp(3) <= 3 * Q_SB, "phase W layout");

constexpr int Q_WOT = Q_EOFF + 4096;

__device__ unsigned g_epoch;
__device__ __align__(1024) unsigned g_bar[4][16][32];
__device__ __align__(1024) uint4 g_wop[8][80][10][8];
__device__ __align__(1024) uint4 g_csp[8][16][96];
__device__ __align__(1024) uint4 g_stp[16][8][64];
__device__ __align__(1024) uint4 g_sp2[16][8][8][8];
__device__ __align__(1024) uint4 g_halo[128][2][5][32];

struct Bars { uint64_t full[Q_ST], empty[Q_ST], wfull[3], ex[7], res, go, qdone, prep, hdone, idx, fdone0, att[2], wfree, soon[2], fdone1, st[4], kfree, staged, xland[4], ardy[3], spec; };
constexpr int NBAR = sizeof(Bars) / 8;
struct OBars { uint64_t full[8], ready[8], empty[8]; };
struct Misc { float cs[240], mean[2][64], rstd[2][72]; Bars bar[2]; OBars ob; KgShared kg; uint32_t epoch, pad; };
#define MISC(f) (sb + Q_MISC + (uint32_t)offsetof(Misc, f))
constexpr int Q_SMEM = Q_MISC + sizeof(Misc) + TS_SMEM;
__host__ __device__ constexpr int bar_count(int i) {
#define BAR_IS(f) (i == offsetof(Bars, f) / 8)
    return (i >= 4 && i < 8) ? 16 : (BAR_IS(go) || (i >= offsetof(Bars, att) / 8 && i < offsetof(Bars, st) / 8)) ? 4 : (BAR_IS(qdone) || BAR_IS(fdone0)) ? 8 : BAR_IS(prep) ? 96 :
           BAR_IS(hdone) ? 6 : BAR_IS(kfree) ? 24 : BAR_IS(staged) ? 2 : 1;
}
__device__ __forceinline__ void grid_wait(const unsigned* c, int n, unsigned target, int lane) {
    const unsigned* p = c + 32 * min(lane, n - 1);
    unsigned v;
    int spin = 0;
    do { asm volatile("ld.relaxed.gpu.global.u32 %0, [%1];" : "=r"(v) : "l"(p) : "memory"); } while (!__all_sync(~0u, (int)(v - target) >= 0) && ++spin < (1 << 18));
    fence_acquire();
}
__device__ __forceinline__ void grid_arrive(unsigned* c) {
    fence_release();
    asm volatile("red.relaxed.gpu.global.add.u32 [%0], 1;" ::"l"(c) : "memory");
}

#define TMAP(n) ([] { const CUtensorMap* p_; asm volatile("{\n.reg .b64 t;\nmov.b64 t, fused_kernel_param_" #n ";\ncvta.param.u64 %0, t;\n}" : "=l"(p_)); return p_; }())
extern "C" __global__ void __launch_bounds__(384, 1)
fused_kernel(const SsmParams sp, const __grid_constant__ CUtensorMap mX0, const __grid_constant__ CUtensorMap mX1, const __grid_constant__ CUtensorMap mW,
             const __grid_constant__ CUtensorMap mWr,
             const __grid_constant__ CUtensorMap mRes0, const __grid_constant__ CUtensorMap mRes1, const __grid_constant__ CUtensorMap mOut,
             const __grid_constant__ CUtensorMap mWo, const __grid_constant__ CUtensorMap mFin, const __grid_constant__ CUtensorMap mResA) {
    extern __shared__ __align__(1024) char smraw[];
    const uint32_t sb = s2u(smraw);
    int tid, warp, lane, bx, rank, blk, hg, rot, c0;
    int role;
    {
        const int c = blockIdx.x >> 1, d = c - 41, r = d >= 21 ? 3 : d >= 14 ? 2 : d >= 7 ? 1 : 0;
        const int gp = c < 4 ? 0 : c <= 40 ? (c + 7) & 7 : d - 7 * r + 1;
        const int k = c < 4 ? c : c <= 40 ? (c >> 3) + (gp == 0 ? 3 : gp >= 3 && gp < 7 ? 0 : -1) : (gp >= 3 ? 5 : 4) + r;
        role = G_MAP == 1 ? 16 * k + 2 * gp + (blockIdx.x & 1) : G_MAP == 2 ? 16 * gp + 2 * k + (blockIdx.x & 1) : blockIdx.x;
    }
    auto indices = [&] {
        asm volatile("mov.u32 %0, %%tid.x;" : "=r"(tid));
        asm volatile("mov.u32 %0, %1;" : "=r"(bx) : "r"(role));
        warp = __shfl_sync(~0u, tid >> 5, 0); lane = tid & 31;
        rank = bx & 1; blk = bx & 15; hg = bx >> 4;
        const int u = ((blk >> 1) + hg) & 7;
        rot = (5 * u) >> 2; c0 = 16 * (u & 3);
    };
    indices();
    TS_DECL;
    TS_BEGIN;
#define EPOCH lds32(MISC(epoch))
    int layer = 0;
    uint32_t bars = MISC(bar);
#define BAR(f) (bars + (uint32_t)offsetof(Bars, f))
    auto chunk = [&](int it, int s0) {
        const int i = it < s0 ? it : it - 2;
        return (it >> 1) == (s0 >> 1) ? rot + (it & 1) : i < rot ? i : i + 2;
    };
    auto osrc_of = [&](int j) { return j == 0 ? hg : j - 1 < hg ? j - 1 : j; };
    auto issue_w = [&](uint32_t bb, int it, int lay) {
        const int half = rank;
        const int s = it & (Q_ST - 1);
        const uint32_t fb = bb + 8 * s, db = sb + s * Q_SB + Q_AB + half * 15360;
        const int k0 = chunk(it, Q_SP * lay) * 64 + half * 32;
#pragma unroll
        for (int p = 0; p < 3; p++) tma2d_mc(db + p * 4096, TMAP(3), p * DM + hg * 80, k0, fb, 3);
        tma3d_mc(db + 12288, TMAP(4), hg * 80 + 64, k0, 0, fb, 3);
    };
    auto issue_x = [&](int it) {
        const int s = it & (Q_ST - 1), kc = chunk(it, Q_SP * layer);
        mbar_expect(BAR(full) + 8 * s, Q_SB);
        tma3d(sb + s * Q_SB, TMAP(1) + layer, (layer ? blk : kc) * 64, (layer ? kc : blk) * 64, 0, BAR(full) + 8 * s);
    };
    {
        KgParams kp;
        const uint32_t epoch0 = ldg32(sp.epoch);
        kgen_load(kp, bx, warp, lane, sp);
        if (warp < 8) {
            cluster_arrive_relaxed();
        } else {
            if (elect_one()) {
                if (warp < 10) { prefetch_tmap(TMAP(3)); prefetch_tmap(TMAP(4)); } else prefetch_tmap(warp == 10 ? TMAP(1) : TMAP(8));
                const uint32_t b0 = bars + (warp >= 10 ? sizeof(Bars) : 0);
                if (warp & 1) {
#pragma unroll
                    for (int i = 0; i < NBAR / 2; i++) mbar_init(b0 + i * 8, bar_count(i));
                } else {
#pragma unroll
                    for (int i = NBAR / 2; i < NBAR; i++) mbar_init(b0 + i * 8, bar_count(i));
                }
                fence_mbar_init();
            }
            __syncwarp();
            cluster_arrive_relaxed();
            TS(29);
            cluster_wait();
            TS(27);
            if (elect_one()) {
                if (warp < 10) {
                    issue_w(BAR(full), warp - 8, 0);
                } else if (warp == 10) {
                    issue_x(0); issue_x(1);
                    prefetch_l2((const char*)c_fft + bx * (sizeof(c_fft) / 128), sizeof(c_fft) / 128);
                } else {
                    mbar_expect(BAR(idx), 8192 + 6400);
                    asm volatile("cp.async.bulk.tensor.4d.shared::cluster.global.mbarrier::complete_tx::bytes [%0], [%1, {0, 0, %3, %4}], [%2];"
                                 ::"r"(sb + Q_WOT), "l"(TMAP(8)), "r"(BAR(idx)), "r"(10 * hg), "r"(5 * blk) : "memory");
                    bulk_g2s(sb + F_S23, c_fft + 18 * 512, 8192, BAR(idx));
                }
            }
            __syncwarp();
            TS(30);
        }
        indices();
        kgen_tables(kp, sb + Q_KG, sb + Q_KDUMP, MISC(kg), warp, lane, [&] { if (warp < 8) cluster_wait(); } TS_PASS);
        __syncwarp();
        if (lane == 0) { mbar_arrive_cta(BAR(kfree), 0); mbar_arrive_cta(BAR(kfree), 1); }
        if (warp >= 8) {
            const int t2 = tid - 256;
            float csum[10];
            if (warp < 11 && elect_one()) {
#pragma unroll
                for (int i = 0; i < 8; i++) mbar_init(MISC(ob) + (warp - 8) * 64 + i * 8, warp == 10 ? 4 : 1);
                fence_mbar_init();
            }
            __syncwarp();
            if (t2 == 0) sts32(MISC(epoch), epoch0);
            if (t2 < 64) stg128(&g_sp2[blk][hg][0][0] + t2, make_uint4(0, 0, 0, 0));
            if (t2 >= 64 && t2 < 80) stg128(&g_of[hg][blk][640 * ((t2 >> 3) & 1) + 8 * (73 + (t2 & 6)) + 6 + (t2 & 1)], make_uint4(epoch0, epoch0, epoch0, epoch0));
            if (t2 >= 120) stg128((uint4*)g_fs + 8 * bx + t2 - 120, make_uint4(0, 0, 0, 0));
#pragma unroll
            for (int i = 0; i < 2; i++)
                if (t2 + 128 * i < 192) stg128(g_x1T + (uint32_t)cta_channel(bx, 4 * i + 1 + 2 * (t2 >> 6)) * XP + 32 * (t2 & 62) + 48 + 8 * (t2 & 1), make_uint4(0, 0, 0, 0));
#pragma unroll
            for (int i = 0; i < 3; i++)
                if (t2 + 128 * i < 320) stg128(&g_halo[bx][0][0][0] + t2 + 128 * i, make_uint4(0, 0, 0, 0));
            named_bar(13, 128);
            if (warp > 8) {
                const int hw = warp - 9, mi = lane >> 3, mj = lane & 7;
                mbar_wait(BAR(idx), 0);
                if (hw == 2 && elect_one()) { bulk_s2g(&g_wop[hg][5 * blk], sb + Q_WOT, 6400); bulk_commit(); }
                __syncwarp();
                mbar_wait(BAR(full), 0);
                mbar_wait(BAR(full) + 8, 0);
#pragma unroll
                for (int f = 0; f < 10; f++) csum[f] = 0.f;
#pragma unroll K_CSU
                for (int G = 0; G < 5; G++) {
                    const int row = c0 + 40 * rank + 8 * G + mj;
                    const uint32_t b = sb + (row >> 6) * Q_SB + Q_AB + ((row >> 5) & 1) * 15360;
                    uint32_t r[10];
                    ldsm_x4_t(r[0], r[1], r[2], r[3], b + hw * 4096 + (row & 31) * 128 + ((mi ^ mj) << 4));
                    ldsm_x4_t(r[4], r[5], r[6], r[7], b + hw * 4096 + (row & 31) * 128 + (((4 + mi) ^ mj) << 4));
                    ldsm_x2_t(r[8], r[9], b + 12288 + hw * 1024 + (row & 31) * 32 + (((mi & 1) ^ (mj >> 2)) << 4));
#pragma unroll
                    for (int f = 0; f < 10; f++) csum[f] += bf_lo(r[f]) + bf_hi(r[f]);
                }
                const int q = lane & 3;
                float t[3];
#pragma unroll
                for (int j = 0; j < 3; j++) {
                    float v[4];
#pragma unroll
                    for (int k = 0; k < 4; k++) v[k] = 4 * j + k < 10 ? csum[4 * j + k] : 0.f;
                    const float a0 = ((q & 2) ? v[2] : v[0]) + __shfl_xor_sync(~0u, (q & 2) ? v[0] : v[2], 2);
                    const float a1 = ((q & 2) ? v[3] : v[1]) + __shfl_xor_sync(~0u, (q & 2) ? v[1] : v[3], 2);
                    t[j] = ((q & 1) ? a1 : a0) + __shfl_xor_sync(~0u, (q & 1) ? a0 : a1, 1);
                }
                st_ll4(&g_csp[hg][blk][tid - 288], ~EPOCH & 1u, __float_as_uint(t[0]), __float_as_uint(t[1]), __float_as_uint(t[2]));
            }
        }
        TS(1);
    }

    uint4 fa1[4], ftw[4];
    auto conv_tables = [&] {
#pragma unroll
        for (int i = 0; i < 4; i++) { fa1[i] = ldg_tab(i, tid & 127); ftw[i] = ldg_tab(8 + i, tid & 127); }
    };
    if (warp >= 8) {
    asm volatile("setmaxnreg.dec.sync.aligned.u32 %0;" ::"n"(504 - 2 * R_CONS));
    uint32_t ophase = 0;
#pragma unroll 1
    for (; layer < 2; layer++, bars += sizeof(Bars)) {
        indices();
        TS_PHASE(2 * layer);
        if (layer) {
            const int i = warp - 8, g = lane >> 2;
            const uint32_t eb = ~EPOCH, a = sb + i * Q_SB + g * 128 + (((2 * (lane & 3)) ^ g) << 4) + 2 * (g & 6);
            const unsigned* pp = g_xcnt[chunk(i, Q_SP)][(blk < 8 ? blk : 15 - blk) >> 1];
            mbar_wait(BAR(fdone0) - sizeof(Bars), 0);
            if (i == 3) mbar_wait(BAR(fdone1) - sizeof(Bars), 0);
            if (X_ARR == 0 && i == 3 && elect_one()) grid_arrive(g_bar[2][hg]);
            __syncwarp();
            uint32_t bad;
            int spin = 0;
            do { asm volatile("ld.relaxed.gpu.global.u32 %0, [%1];" : "=r"(bad) : "l"(pp) : "memory"); } while ((int)(bad + 64 * eb) < 0 && ++spin < (1 << 18));
            if (X_DELAY) { const long long t0 = clock64(); while (clock64() - t0 < X_DELAY) {} }
            fence_async_global();
            TS(1);
            spin = 0;
            do {
                if (elect_one()) {
                    mbar_expect(BAR(xland) + 8 * i, Q_AB);
                    tma3d(sb + i * Q_SB, TMAP(2), blk * 64, chunk(i, Q_SP) * 64, 0, BAR(xland) + 8 * i);
                    if (X_ARR == 1 && i == 3 && spin == 0) grid_arrive(g_bar[2][hg]);
                }
                __syncwarp();
                mbar_wait(BAR(xland) + 8 * i, spin & 1);
                bad = 0;
#pragma unroll
                for (int k = 0; k < 16; k++) bad |= lds32(a + k * 1024) ^ eb;
            } while (__any_sync(~0u, bad & 1u) && ++spin < (1 << 16));
            if (lane == 0) mbar_expect(BAR(full) + 8 * i, Q_BB);
            TS(9);
        }
        if (warp == 8) {
            if (layer) {
                grid_wait(g_bar[2][0], 8, 16 * (EPOCH + 1), lane);
                fence_async_global();
                TS(10);
            }
            if (elect_one()) {
#pragma unroll 1
                for (int it = 2 + 2 * layer; it < 10; it++) {
                    if (it >= Q_ST) mbar_wait(BAR(empty) + 8 * (it & (Q_ST - 1)), ((it >> 2) - 1) & 1);
                    else mbar_wait(BAR(kfree), 0);
                    if (it == Q_ST + Q_SP * layer) mbar_wait(BAR(hdone), 0);
                    issue_x(it);
                    issue_w(BAR(full), it, layer);
                    if (it == Q_SP + 1) mbar_arrive(BAR(spec));
                }
                { prefetch_tmap(TMAP(5) + layer); prefetch_tmap(TMAP(7)); prefetch_tmap(TMAP(10)); }
                if (layer == 0) { mbar_wait(BAR(prep), 0); fence_async_global(); }
#pragma unroll 1
                for (int j = 0; j < 8; j++) {
                    const int b = (j + 1) >> 2;
                    const uint32_t fb = BAR(wfull) + 8 * b;
                    if (j == 0 || j == 3 || j == 7) {
                        mbar_wait(BAR(empty) + 8 * ((2 + b) & 3), b < 2);
                        TS(11 + b);
                        mbar_expect(fb, (b == 0 ? 3 : b == 1 ? 4 : 1) * 12800);
                    }
                    bulk_g2s_mc(sb + w_grp(j) + rank * 6400, &g_wop[hg][osrc_of(j) * 10 + rank * 5], 6400, fb, 3);
                }
                mbar_expect(BAR(res), 20480);
                if (layer) {
                    tma3d(sb + W_RES, TMAP(6), blk * 64, hg * 80, 0, BAR(res));
                } else {
#pragma unroll 1
                    for (int p = 0; p < 2; p++) {
                        tma3d(sb + W_RES + p * 10240, TMAP(10), hg * 80, blk * 64, p, BAR(res));
                        tma3d(sb + W_RES + p * 10240 + 8192, TMAP(5), hg * 80 + 64, blk * 64, p, BAR(res));
                    }
                }
            }
            __syncwarp();
        } else {
            const int ht = tid - 288, hw = warp - 9, mi = lane >> 3, mj = lane & 7, g = lane >> 2, q = lane & 3;
            auto F = [](uint32_t x) { return __uint_as_float(x); };
            auto U = [](float x) { return __float_as_uint(x); };
            const uint32_t lb = layer ^ 1, eb = ~EPOCH & 1u;
            if (layer) mbar_wait(BAR(spec), 0);
            mbar_wait(BAR(full), layer);
            mbar_wait(BAR(full) + 8, layer);
            if (ht == 0) TSX(2, 2);
            uint32_t xf[3][20];
#pragma unroll
            for (int i = 0; i < 3; i++) {
                const int tile = min(hw + 3 * i, 7);
#pragma unroll
                for (int k = 0; k < 5; k++) {
                    const int ch = c0 + 16 * k + 8 * (mi >> 1), tok = 16 * (tile & 3) + 8 * (mi & 1);
                    const uint32_t a = sb + (ch >> 6) * Q_SB + (tile >> 2) * 8192;
                    if (layer == 0) ldsm_x4(xf[i][4 * k], xf[i][4 * k + 1], xf[i][4 * k + 2], xf[i][4 * k + 3], a + (tok + mj) * 128 + ((((ch & 63) >> 3) ^ mj) << 4));
                    else ldsm_x4_t(xf[i][4 * k], xf[i][4 * k + 1], xf[i][4 * k + 2], xf[i][4 * k + 3], a + ((ch & 63) + mj) * 128 + (((tok >> 3) ^ mj) << 4));
                }
            }
            fence_async_smem();
            __syncwarp();
            if (lane == 0) { mbar_arrive_cta(BAR(hdone), 0); mbar_arrive_cta(BAR(hdone), 1); }
            if (ht == 0) TSX(2, 3);
            if (layer == 0) {
                if (hw == 2 && elect_one()) { bulk_wait(); fence_async_global(); grid_arrive(g_bar[3][hg]); }
                __syncwarp();
                mbar_wait(BAR(kfree), 0);
            }
            if (ht == 0) TSX(2, 8);
#pragma unroll 1
            for (int tile = hw; tile < 8; tile += 3) {
                float a[4] = {0.f, 0.f, 0.f, 0.f};
#pragma unroll
                for (int j = 0; j < 20; j++) {
                    const float lo = bf_lo(xf[0][j]), hi = bf_hi(xf[0][j]);
                    a[2 * (j & 1)] += lo + hi; a[2 * (j & 1) + 1] = fmaf(lo, lo, fmaf(hi, hi, a[2 * (j & 1) + 1]));
                    xf[0][j] = xf[1][j]; xf[1][j] = xf[2][j];
                }
#pragma unroll
                for (int j = 0; j < 4; j++) { a[j] += __shfl_xor_sync(~0u, a[j], 1); a[j] += __shfl_xor_sync(~0u, a[j], 2); }
                if (q == 0) st_ll4(&g_stp[blk][hg][8 * tile + g], (U(a[0]) & ~1u) | lb, U(a[1]), U(a[2]), U(a[3]));
            }
            if (ht == 0) TSX(2, 4);
            if (layer == 0) {
                float t[4] = {0.f, 0.f, 0.f, 0.f};
                uint4 v[16];
                int spin = 0;
                uint32_t bad;
                do {
                    bad = 0;
#pragma unroll
                    for (int j = 0; j < 16; j++) v[j] = ld_ll4(&g_csp[hg][j][ht]);
#pragma unroll
                    for (int j = 0; j < 16; j++) bad |= v[j].x ^ eb;
                } while ((bad & 1u) && ++spin < (1 << 18));
#pragma unroll
                for (int j = 0; j < 16; j++) { t[0] += F(v[j].y); t[1] += F(v[j].z); t[2] += F(v[j].w); }
#pragma unroll
                for (int j = 0; j < 3; j++) if (q + 4 * j < 10) sts32(MISC(cs) + 4 * (80 * hw + 20 * (g >> 1) + 2 * (q + 4 * j) + (g & 1)), U(t[j]));
                if (hw == 2) grid_wait(g_bar[3][0], 8, 16 * (EPOCH + 1), lane);
            }
            if (ht == 0) TSX(2, 15);
            if (ht < 80) {
                const bool halo = ht >= 64;
                const int p = halo ? (ht >> 3) & 1 : ht >> 5, i = halo ? (ht & 7) - 8 : 8 + 2 * (ht & 24) + (ht & 7);
                const uint4* src = &g_stp[halo && blk ? blk - 1 : blk][0][halo ? 32 * p + 24 + (ht & 7) : ht];
                uint4 v[8];
                int spin = 0;
                uint32_t bad;
                do {
                    bad = 0;
#pragma unroll
                    for (int j = 0; j < 8; j++) v[j] = ld_ll4(src + 64 * j);
#pragma unroll
                    for (int j = 0; j < 8; j++) bad |= v[j].x ^ lb;
                } while ((bad & 1u) && ++spin < (1 << 18));
                float t[4] = {0.f, 0.f, 0.f, 0.f};
#pragma unroll
                for (int j = 0; j < 8; j++) { t[0] += F(v[j].x); t[1] += F(v[j].y); t[2] += F(v[j].z); t[3] += F(v[j].w); }
                const uint32_t s0 = ln_finish_packed(t[0], t[1]), s1 = ln_finish_packed(t[2], t[3]);
                const uint32_t am = MISC(mean) + 4 * (64 * p + i), ar = MISC(rstd) + 4 * (72 * p + i);
                if (!halo) { sts32(am - 32, U(bf_hi(s0))); sts32(am, U(bf_hi(s1))); sts32(ar, U(frcp(bf_lo(s0)))); }
                sts32(ar + 32, U(frcp(bf_lo(s1))));
            }
            fence_acquire();
            mbar_arrive(BAR(prep));
            if (ht == 0) TSX(2, 5);
        }
        __syncwarp();
        indices();
        {
            const uint4 ko[2] = {ldg_tab(16, tid & 127), ldg_tab(17, tid & 127)};
            conv_tables();
            kernel_stage<1>(ko, sb + Q_KDUMP + 4 * KG_RES, MISC(kg), 4, sb + F_EO + 2 * 8192, warp & 3, lane);
            fence_async_smem();
        }
        {
            const int p = warp & 1;
            const uint32_t fb = EPOCH ^ layer ^ 1, ob = MISC(ob) + 32 * p;
            auto fetch = [&](int j) {
                if (elect_one()) {
                    mbar_expect(ob + 8 * ((j - 1) & 3), 10240);
                    bulk_g2s(sb + o_slot(p, (j - 1) & 3), &g_of[osrc_of(j)][blk][640 * p], 10240, ob + 8 * ((j - 1) & 3));
                }
                __syncwarp();
            };
            if (warp < 10) {
                const uint32_t* pp = &g_of[osrc_of(1 + min(lane >> 2, 6))][blk][640 * p + 8 * (73 + 2 * (lane & 3)) + 7].x;
                mbar_wait(BAR(qdone), 0);
                mbar_wait(BAR(att) + 8 * p, 0);
                uint32_t miss = ~0u;
                int spin = 0;
#pragma unroll 1
                for (int j = 1; j < 8; j++) {
                    while (((miss >> (4 * j - 4)) & 15u) && ++spin < (1 << 18)) {
                        uint32_t v;
                        asm volatile("ld.relaxed.gpu.global.u32 %0, [%1];" : "=r"(v) : "l"(pp) : "memory");
                        miss = __ballot_sync(~0u, (v ^ fb) & 1u);
                        fence_async_global();
                    }
                    if (j == 1) TS(16);
                    if (j > 3) mbar_wait(ob + 128 + 8 * ((j - 1) & 3), layer);
                    fetch(j);
                }
                TS(17);
            } else {
#pragma unroll 1
                for (int j = 1, spin = 0; j < 8;) {
                    const int s = (j - 1) & 3;
                    mbar_wait(ob + 8 * s, (ophase >> s) & 1);
                    ophase ^= 1u << s;
                    const uint32_t a = sb + o_slot(p, s) + (lane >> 2) * 132 + (lane & 3) * 32;
                    uint32_t bad = 0;
#pragma unroll
                    for (int i = 0; i < 10; i++) bad |= lds32(a + i * 1024) ^ fb;
                    if (__any_sync(~0u, bad & 1u) && ++spin < (1 << 16)) { fetch(j); continue; }
                    if (lane == 0) mbar_arrive(ob + 64 + 8 * s);
                    j++;
                }
            }
        }
        TS_PHASE(2 * layer + 1);
        TS(0);
        indices();
        named_bar(3, 128);
        conv_wg<1>(cta_channel(bx, 4), layer, sb + F_EO + 2 * 8192, sb + 2 * Q_SB, sb + F_S23, MISC(kg.kexp) + 16, MISC(epoch), sb, BAR(st), BAR(ardy) + 16, 0,
                   warp, lane, fa1, ftw,
        [&] {
            if (warp == 9) {
                auto F = [](uint32_t x) { return __uint_as_float(x); };
                mbar_wait(BAR(soon) + 8 * (hg >> 2), 0);
                TS(23);
                const uint4* src = &g_sp2[blk][hg][0][0] + lane;
                uint4* dst = (uint4*)(g_fs[(lane >> 2) & 1] + 1024 * (hg >> 2) + 64 * blk + 16 * (hg & 3)) + (lane & 3);
                const bool up = lane & 8;
#pragma unroll 1
                for (int spin = 0; spin < (1 << 18); spin++) {
                    const uint4 a = ld_ll4(src), b = ld_ll4(src + 32);
                    const bool ok = !__any_sync(~0u, ~((a.x ^ layer) & (b.x ^ layer)) & 1u);
                    const float s0 = F(a.x) + F(b.x), q0 = F(a.y) + F(b.y), s1 = F(a.z) + F(b.z), q1 = F(a.w) + F(b.w);
                    float sm = (up ? s1 : s0) + __shfl_xor_sync(~0u, up ? s0 : s1, 8), sq = (up ? q1 : q0) + __shfl_xor_sync(~0u, up ? q0 : q1, 8);
                    sm += __shfl_xor_sync(~0u, sm, 16); sq += __shfl_xor_sync(~0u, sq, 16);
                    const float m = sm * (1.0f / DM), r = frsq(fmaxf(fmaf(sq, 1.0f / DM, fmaf(-m, m, 1e-5f)), 1e-5f));
                    const uint32_t v = __float_as_uint(lane & 16 ? -m * r : r);
                    const uint32_t v0 = __shfl_sync(~0u, v, 4 * lane), v1 = __shfl_sync(~0u, v, 4 * lane + 1), v2 = __shfl_sync(~0u, v, 4 * lane + 2), v3 = __shfl_sync(~0u, v, 4 * lane + 3);
                    if (ok && lane < 8) st_ll4(dst, (v0 & ~1u) | (layer ^ 1), v1, v2, v3);
                    if (ok) break;
                }
            }
            TS(25);
            mbar_wait(BAR(staged), 0);
        }, [&] {
            if (tid == 352) prefetch_tmap(layer ? TMAP(9) : TMAP(2));
        } TS_PASS);
        named_bar(3, 128);
        TS(20);
    }
    } else {
#pragma unroll 1
    for (; layer < 2; layer++, bars += sizeof(Bars)) {
    indices();
    TS_PHASE(2 * layer);
    const int wg = warp >> 2, w = warp & 3;
    const int mi = lane >> 3, mj = lane & 7, g = lane >> 2, q = lane & 3;
    TS(2);
    float acc[120];
#pragma unroll
    for (int i = 0; i < 120; i++) acc[i] = 0.f;
    auto release = [&](int it) {
        if (lane == 0) { mbar_arrive_cta(BAR(empty) + 8 * (it & (Q_ST - 1)), 0); mbar_arrive_cta(BAR(empty) + 8 * (it & (Q_ST - 1)), 1); }
    };
#pragma unroll 1
    for (int it = 0; it < 10; it++) {
        const int s = it & (Q_ST - 1);
        const uint32_t st = sb + s * Q_SB;
        const bool hold = wg == 1 && it == Q_S0;
        if (hold) {
            wg_wait<0>();
            release(it - 1);
            mbar_wait(BAR(go), 0);
        }
        mbar_wait(BAR(full) + 8 * (s), (it >> 2) & 1);
        if (it < 2) TS(3 + it);
        if (it == 6) TS(5);
        if (it == 9) TS(6);
        const uint64_t da = mkdesc(st + wg * 8192, 16, 1024, 1);
        const uint64_t db = mkdesc(st + Q_AB, 4096, 1024, 1);
        const uint64_t dr = mkdesc(st + Q_AB + 12288, 1024, 256, 3);
        if (layer == 0) {
            wg_fence();
#pragma unroll
            for (int ks = 0; ks < 4; ks++) {
                const int sc = 1;
                wgmma_n192<0, 1>(*(float(*)[96]) & acc[0], da + ks * 2, db + (ks >> 1) * 960 + (ks & 1) * 128, sc);
                wgmma_n48<0, 1>(*(float(*)[24]) & acc[96], da + ks * 2, dr + (ks >> 1) * 960 + (ks & 1) * 32, sc);
            }
            wg_commit();
        } else {
            wg_fence();
#pragma unroll
            for (int ks = 0; ks < 4; ks++) {
                const int sc = 1;
                wgmma_n192<1, 1>(*(float(*)[96]) & acc[0], da + ks * 128, db + (ks >> 1) * 960 + (ks & 1) * 128, sc);
                wgmma_n48<1, 1>(*(float(*)[24]) & acc[96], da + ks * 128, dr + (ks >> 1) * 960 + (ks & 1) * 32, sc);
            }
            wg_commit();
        }
        wg_wait<1>();
        if (it > 0 && !hold) release(it - 1);
    }
    if (wg == 0 && lane == 0) mbar_arrive(BAR(go));
    asm volatile("setmaxnreg.inc.sync.aligned.u32 %0;" ::"n"(R_CONS));
    mbar_wait(BAR(prep), 0);
    const uint32_t ob = layer ^ 1;
    const bool first = (blk == 0 && w == 0);
    const bool sel0 = (2 * q > g), sel1 = (2 * q + 1 > g);
    constexpr float SC = 0.22360679774997896f * 1.4426950408889634f;
    const float m0 = __uint_as_float(lds32(MISC(mean) + 4 * (16 * warp + g))), m1 = __uint_as_float(lds32(MISC(mean) + 4 * (16 * warp + g + 8)));
    uint4 cs[3][5];
    auto cs_load = [&](int p) {
#pragma unroll
        for (int i = 0; i < 5; i++) cs[p][i] = lds128(MISC(cs) + 4 * (80 * p + 20 * q + 4 * i));
    };
    cs_load(1); cs_load(2);
    wg_wait<0>();
    TS(7);
    if (lane == 0) mbar_arrive(BAR(qdone));
    uint32_t ql[10], qh[10], kl[10], kh[10], vl[10], vh[10];
    auto fold = [&](int p, int f, int h) {
        const int j = (f < 8) ? 8 * p + f : 24 + 2 * p + (f - 8);
        const float c0 = __uint_as_float(u4(cs[p][f >> 1], 2 * (f & 1))), c1 = __uint_as_float(u4(cs[p][f >> 1], 2 * (f & 1) + 1));
        const float m = h ? m1 : m0;
        return pack2(fmaf(-m, c0, acc[4 * j + 2 * h]), fmaf(-m, c1, acc[4 * j + 2 * h + 1]));
    };
#pragma unroll
    for (int f = 0; f < 10; f++) { vh[f] = fold(2, f, 1); if (f < A_VLO) vl[f] = fold(2, f, 0); }
#pragma unroll
    for (int f = 0; f < 10; f++) kh[f] = fold(1, f, 1);
#pragma unroll
    for (int f = 0; f < A_VLO; f++) asm volatile("" : "+r"(vl[f]));
    {
        const uint32_t mk = w == 3 ? 1u : 0u;
        auto mark = [&](uint32_t& v) { v = (v & ~mk) | (ob & mk); };
        mark(kh[0]); mark(kh[5]); mark(vh[0]); mark(vh[4]); mark(vh[8]);
    }
    if (w == 3) {
        uint4* hp = &g_halo[bx][wg][0][lane];
        st_ll4(hp, kh[0], kh[1], kh[3], kh[4]); st_ll4(hp + 32, kh[5], kh[6], kh[8], kh[9]);
        st_ll4(hp + 64, vh[0], vh[1], vh[2], vh[3]); st_ll4(hp + 96, vh[4], vh[5], vh[6], vh[7]);
        st_ll4(hp + 128, vh[8], vh[9], kh[2], kh[7]);
    } else {
        const uint32_t a = sb + Q_EOFF + wg * 8192 + w * Q_ESLOT + mj * Q_EROW + mi * 16;
        stsm_x4(a, kh[0], kh[1], kh[3], kh[4]);
        stsm_x4(a + 64, kh[5], kh[6], kh[8], kh[9]);
        stsm_x4(a + 128, vh[0], vh[1], vh[2], vh[3]);
        stsm_x4(a + 192, vh[4], vh[5], vh[6], vh[7]);
        stsm_x4(a + 256, vh[8], vh[9], kh[2], kh[7]);
        __syncwarp();
        if (lane == 0) mbar_arrive(BAR(ex) + 8 * warp);
    }
    TS(9);
    cs_load(0);
#pragma unroll
    for (int f = 0; f < 10; f++) { kl[f] = fold(1, f, 0); if (f >= A_VLO) vl[f] = fold(2, f, 0); }
#pragma unroll
    for (int f = 0; f < 10; f++) { ql[f] = fold(0, f, 0); qh[f] = fold(0, f, 1); }
    auto rs = [&](int i) { return __uint_as_float(lds32(MISC(rstd) + 4 * (72 * wg + 16 * w + i))); };
    const float kx0 = rs(2 * q + (sel0 ? 0 : 8)), kx1 = rs(2 * q + (sel1 ? 1 : 9)), ky0 = rs(2 * q + (sel0 ? 8 : 16)), ky1 = rs(2 * q + (sel1 ? 9 : 17));
    const float rx = SC * rs(8 + g), ry = SC * rs(16 + g), cx0 = rx * kx0, cx1 = rx * kx1, cy0 = ry * ky0, cy1 = ry * ky1;
    uint4 hv[5];
    const uint4* hp = &g_halo[bx - 1][wg][0][lane];
    auto prev = [&] {
        if (w > 0) {
            const uint32_t a = sb + Q_EOFF + wg * 8192 + (w - 1) * Q_ESLOT + mj * Q_EROW + mi * 16;
            mbar_wait(BAR(ex) + 8 * (warp - 1), 0);
            ldsm_x4(hv[0].x, hv[0].y, hv[0].z, hv[0].w, a);
            ldsm_x4(hv[1].x, hv[1].y, hv[1].z, hv[1].w, a + 64);
            ldsm_x4_t(hv[2].x, hv[2].y, hv[2].z, hv[2].w, a + 128);
            ldsm_x4_t(hv[3].x, hv[3].y, hv[3].z, hv[3].w, a + 192);
            ldsm_x2_t(hv[4].x, hv[4].y, a + 256);
            ldsm_x2(hv[4].z, hv[4].w, a + 288 - (lane >> 4) * 32);
        } else if (blk > 0) {
#pragma unroll
            for (int f = 0; f < 5; f++) hv[f] = ld_ll4(hp + 32 * f);
        } else {
#pragma unroll
            for (int f = 0; f < 5; f++) hv[f] = make_uint4(0, 0, 0, 0);
        }
    };
    uint32_t vt[10][2];
#pragma unroll
    for (int f = 0; f < 10; f++) { vt[f][0] = movm_t(vl[f]); vt[f][1] = movm_t(vh[f]); }
    prev();
    TS(10);
    auto FA = [](int h) { return h == 0 ? 0 : h == 1 ? 3 : h == 2 ? 5 : 8; };
    auto FH = [](int h) { return h < 2 ? 2 : 7; };
    const uint32_t pm = (sel0 ? 0xFFFFu : 0u) | (sel1 ? 0xFFFF0000u : 0u);
    auto softmax = [&](float x0, float x1, float k0, float k1) {
        float mx = fmaxf(x0, x1);
        mx = fmaxf(mx, __shfl_xor_sync(~0u, mx, 1));
        mx = fmaxf(mx, __shfl_xor_sync(~0u, mx, 2));
        x0 = ex2(x0 - mx); x1 = ex2(x1 - mx);
        float sx = x0 + x1;
        sx += __shfl_xor_sync(~0u, sx, 1);
        sx += __shfl_xor_sync(~0u, sx, 2);
        const float ix = frcp(sx);
        return pack2(x0 * k0 * ix, x1 * k1 * ix);
    };
    uint32_t qm[4][2], py[4];
    float sl[4][2];
#pragma unroll
    for (int h = 0; h < 4; h++) {
        const int fa = FA(h), fb = fa + 1, fh = FH(h);
        const bool mine = (h & 1) ? (q >= 2) : (q < 2);
        qm[h][0] = mine ? ql[fh] : 0u; qm[h][1] = mine ? qh[fh] : 0u;
        float S1[4] = {0.f, 0.f, 0.f, 0.f}, S2[4] = {0.f, 0.f, 0.f, 0.f};
        mma16816(S1, ql[fa], qh[fa], ql[fb], qh[fb], kl[fa], kl[fb]); mma1688(S1, qm[h][0], qm[h][1], kl[fh]);
        mma16816(S2, ql[fa], qh[fa], ql[fb], qh[fb], kh[fa], kh[fb]); mma1688(S2, qm[h][0], qm[h][1], kh[fh]);
        sl[h][0] = S1[0]; sl[h][1] = S1[1];
        py[h] = softmax((sel0 ? S1[2] : S2[2]) * cy0, (sel1 ? S1[3] : S2[3]) * cy1, ky0, ky1);
    }
    TS(11);
    if (w == 0 && blk > 0) {
        ll_check5(hv, hp, ob);
#pragma unroll
        for (int f = 2; f < 4; f++) hv[f] = make_uint4(movm_t(hv[f].x), movm_t(hv[f].y), movm_t(hv[f].z), movm_t(hv[f].w));
        hv[4].x = movm_t(hv[4].x); hv[4].y = movm_t(hv[4].y);
    }
    const uint32_t kp[10] = {hv[0].x, hv[0].y, hv[4].z, hv[0].z, hv[0].w, hv[1].x, hv[1].y, hv[4].w, hv[1].z, hv[1].w};
    const uint32_t vp[10] = {hv[2].x, hv[2].y, hv[2].z, hv[2].w, hv[3].x, hv[3].y, hv[3].z, hv[3].w, hv[4].x, hv[4].y};
    TS(12);
    const uint4 ko[2] = {ldg_tab(16, tid & 127), ldg_tab(17, tid & 127)};
    const float bx0 = first && sel0 ? -INFINITY : 0.f, bx1 = first && sel1 ? -INFINITY : 0.f;
    float oacc[10][4];
#pragma unroll
    for (int h = 0; h < 4; h++) {
        const int fa = FA(h), fb = fa + 1, fh = FH(h);
        const bool mine = (h & 1) ? (q >= 2) : (q < 2);
        float S0[4] = {0.f, 0.f, 0.f, 0.f};
        mma16816(S0, ql[fa], qh[fa], ql[fb], qh[fb], kp[fa], kp[fb]); mma1688(S0, qm[h][0], qm[h][1], kp[fh]);
        const uint32_t px = softmax(fmaf(sel0 ? S0[0] : sl[h][0], cx0, bx0), fmaf(sel1 ? S0[1] : sl[h][1], cx1, bx1), kx0, kx1);
#pragma unroll
        for (int i = 0; i < 3; i++) {
            const int f = (i == 0) ? fa : (i == 1) ? fb : fh;
            float O[4] = {0.f, 0.f, 0.f, 0.f};
            mma16816(O, px & ~pm, py[h] & pm, 0u, py[h] & ~pm, vt[f][0], vt[f][1]);
            mma1688(O, px & pm, 0u, vp[f]);
            if (i < 2 || !(h & 1) || mine) { oacc[f][0] = O[0]; oacc[f][1] = O[1]; oacc[f][2] = O[2]; oacc[f][3] = O[3]; }
        }
    }
    TS(13);
    float aw[40];
    uint4 of[5];
    {
        const uint32_t fb = EPOCH ^ ob, mk[2] = {q == 0 || mj == 2 * w, q == 0 || mj == 2 * w + 1};
        uint32_t* dst = &g_of[hg][blk][640 * wg + 16 * w].x + lane;
#pragma unroll
        for (int i = 0; i < 20; i++) {
            const uint32_t v = (pack2(oacc[i >> 1][2 * (i & 1)], oacc[i >> 1][2 * (i & 1) + 1]) & ~mk[i & 1]) | (fb & mk[i & 1]);
            u4r(of[i >> 2], i & 3) = v;
            asm volatile("st.relaxed.gpu.global.u32 [%0], %1;" ::"l"(dst + 256 * (i >> 1) + 32 * (i & 1)), "r"(v) : "memory");
        }
        if (lane == 0) mbar_arrive(BAR(att) + 8 * wg);
        TS(14);
    }
    const uint32_t obar = MISC(ob) + 32 * wg;
    named_bar(1 + wg, 128);
    kernel_stage<2>(ko, sb + Q_KDUMP + 2 * wg * KG_RES, MISC(kg), 2 * wg, sb + F_EO + wg * 8192, w, lane);
    TS(15);
    uint32_t res[20];
    mbar_wait(BAR(res), 0);
    const uint32_t ta = (8 * (mi >> 1) + mj) * 128 + (((2 * w + (mi & 1)) ^ mj) << 4);
    if (layer == 0) {
        const int tok = 16 * w + 8 * (mi & 1) + mj;
#pragma unroll
        for (int k = 0; k < 4; k++)
            ldsm_x4(res[4 * k], res[4 * k + 1], res[4 * k + 2], res[4 * k + 3], sb + W_RES + wg * 10240 + tok * 128 + (((2 * k + (mi >> 1)) ^ mj) << 4));
        ldsm_x4(res[16], res[17], res[18], res[19], sb + W_RES + wg * 10240 + 8192 + tok * 32 + (((mi >> 1) ^ (mj >> 2)) << 4));
    } else {
#pragma unroll
        for (int k = 0; k < 5; k++) ldsm_x4_t(res[4 * k], res[4 * k + 1], res[4 * k + 2], res[4 * k + 3], sb + W_RES + wg * 10240 + k * 2048 + ta);
    }
    fence_async_smem();
    __syncwarp();
    if (lane == 0) mbar_arrive(obar + 128 + 24);
    {
#pragma unroll
        for (int i = 0; i < 20; i++) { aw[2 * i] = bf_lo(res[i]); aw[2 * i + 1] = bf_hi(res[i]); }
        mbar_wait(BAR(wfull), 0);
        const uint64_t dm = mkdesc(sb + w_grp(0), 1280, 128, 0);
        wg_fence();
#pragma unroll
        for (int k = 0; k < 5; k++) wgmma_rs80(aw, of[k], dm + k * 160, 1);
        wg_commit();
    }
    conv_tables();
    wg_wait<0>();
    TS(8);
#pragma unroll 1
    for (int j = 1; j < 8; j++) {
        const int s = (j - 1) & 3;
        const uint64_t da = mkdesc(sb + o_slot(wg, s), 1024, 128, 0), dm = mkdesc(sb + w_grp(j), 1280, 128, 0);
        if (s == 2) mbar_wait(BAR(wfull) + 2 * (j + 1), 0);
        mbar_wait(obar + 64 + 8 * s, s == 3 ? layer : j > 4);
        if (j == 1) TS(17);
        if (j == 5) TS(18);
        wg_fence();
#pragma unroll
        for (int k = 0; k < 5; k++) wgmma_ss80(aw, da + k * 128, dm + k * 160);
        wg_commit();
        wg_wait<1>();
        if (j > 1 && j < 5 && lane == 0) mbar_arrive(obar + 128 + 8 * (j - 2));
    }
    if (lane == 0) mbar_arrive(BAR(soon) + 8 * wg);
    named_bar(1 + wg, 128);
    wg_wait<0>();
    TS(19);
    {
        float a[2][4] = {{0.f, 0.f, 0.f, 0.f}, {0.f, 0.f, 0.f, 0.f}};
#pragma unroll
        for (int i = 0; i < 40; i++) { a[i & 1][i & 2] += aw[i]; a[i & 1][(i & 2) + 1] = fmaf(aw[i], aw[i], a[i & 1][(i & 2) + 1]); }
#pragma unroll
        for (int j = 0; j < 4; j++) { a[0][j] += a[1][j]; a[0][j] += __shfl_xor_sync(~0u, a[0][j], 1); a[0][j] += __shfl_xor_sync(~0u, a[0][j], 2); }
        if (q == 0) st_ll4(&g_sp2[blk][warp][hg][g], (__float_as_uint(a[0][0]) & ~1u) | ob, __float_as_uint(a[0][1]), __float_as_uint(a[0][2]), __float_as_uint(a[0][3]));
    }
    TS(23);
#pragma unroll
    for (int i = 0; i < 20; i++) res[i] = pack2(aw[2 * i], aw[2 * i + 1]);
    {
        const uint32_t mk = (g & 3) ? 0u : 0x00010001u;
#pragma unroll
        for (int k = 0; k < 5; k++) {
            uint32_t m[4];
#pragma unroll
            for (int i = 0; i < 4; i++) m[i] = (res[4 * k + i] & ~mk) | (mk & (0u - ob));
            stsm_x4_t(sb + w_out(wg) + k * 2048 + ta, m[0], m[1], m[2], m[3]);
        }
        fence_async_smem();
        named_bar(1 + wg, 128);
        if (w == 0 && elect_one()) {
            asm volatile("cp.async.bulk.tensor.2d.global.shared::cta.bulk_group [%0, {%2, %3}], [%1];"
                         ::"l"(TMAP(7)), "r"(sb + w_out(wg)), "r"(1024 * wg + 64 * blk), "r"(hg * 80) : "memory");
            bulk_commit();
            mbar_arrive(BAR(staged));
        }
        __syncwarp();
        TS(20);
    }
    if (layer) {
#pragma unroll
        for (int k = 0; k < 5; k++) stsm_x4_t(sb + W_RES + wg * 10240 + k * 2048 + ta, res[4 * k], res[4 * k + 1], res[4 * k + 2], res[4 * k + 3]);
    }
    TS(22);
    TS_PHASE(2 * layer + 1);
    TS(0);
    indices();
    conv_wg<2>(cta_channel(bx, 2 * (warp >> 2)), layer, sb + F_EO + (warp >> 2) * 8192, sb + (1 + 2 * (warp >> 2)) * Q_SB, sb + F_S23, MISC(kg.kexp) + 8 * (warp >> 2),
               MISC(epoch), sb, BAR(st), BAR(ardy) + 8 * (warp >> 2), BAR(fdone0), warp, lane, fa1, ftw, [&] {
        if ((warp & 3) == 0 && elect_one()) {
            asm volatile("cp.async.bulk.wait_group.read 0;" ::: "memory");
            if (layer == 0) { mbar_arrive_cta(BAR(wfree), 0); mbar_arrive_cta(BAR(wfree), 1); }
        }
        __syncwarp();
        if (warp == 0) mbar_wait(BAR(staged), 0);
    }, [&] {
        if (layer == 0 && warp >= 4 && elect_one()) { mbar_wait(BAR(wfree), 0); issue_w(BAR(full) + sizeof(Bars), warp - 4, 1); }
        __syncwarp();
    } TS_PASS);
    __syncwarp();
    if (lane == 0) mbar_arrive(warp < 4 ? BAR(fdone0) : BAR(fdone1));
    TS(20);
    asm volatile("setmaxnreg.dec.sync.aligned.u32 168;");
    }
    named_bar(1 + (warp >> 2), 128);
    asm volatile("setmaxnreg.dec.sync.aligned.u32 %0;" ::"n"(504 - 2 * R_CONS));
    }
    indices();
    const int cq = 4 * (warp >> 1) + (lane & 3), tg = 8 * (warp & 1) + (lane >> 2);
    const uint32_t fb = ~EPOCH & 1u;
    uint2 xr[4][2];
    __syncthreads();
    if (tid < 320) {
#pragma unroll
        for (int i = 0; i < 8; i++) {
            const int ch = 4 * cq + (i >> 1);
            asm volatile("ld.shared.v2.u32 {%0, %1}, [%2];" : "=r"(xr[i >> 1][i & 1].x), "=r"(xr[i >> 1][i & 1].y)
                         : "r"(sb + W_RES + (i & 1) * 10240 + ch * 128 + (((tg >> 1) ^ (ch & 7)) << 4) + (tg & 1) * 8) : "memory");
        }
    }
    if (tid < 320) {
        const uint4* src = &g_of[hg][blk][64 * cq + tg];
        uint4 v[4];
#pragma unroll
        for (int i = 0; i < 4; i++) v[i] = make_uint4(~fb, 0, 0, 0);
        int spin = 0;
        while (true) {
#pragma unroll
            for (int i = 0; i < 4; i++) if ((v[i].x ^ fb) & 1u) v[i] = ld_ll4(src + 16 * i);
            if (!(((v[0].x ^ fb) | (v[1].x ^ fb) | (v[2].x ^ fb) | (v[3].x ^ fb)) & 1u) || ++spin >= (1 << 18)) break;
        }
        TS(21);
#pragma unroll
        for (int i = 0; i < 16; i++) asm("add.rn.bf16x2 %0, %0, %1;" : "+r"(u4r(v[i >> 2], i & 3)) : "r"((i & 1) ? xr[i >> 2][(i >> 1) & 1].y : xr[i >> 2][(i >> 1) & 1].x));
#pragma unroll
        for (int j = 0; j < 8; j++) {
            const uint32_t sel = (j & 2) ? 0x7632 : 0x5410;
            const int k = 2 * (j & 1) + (j >> 2);
            asm volatile("st.shared.v2.u32 [%0], {%1, %2};" ::"r"(sb + 2 * Q_SB + (16 * j + tg) * 160 + cq * 8),
                         "r"(__byte_perm(u4(v[0], k), u4(v[1], k), sel)), "r"(__byte_perm(u4(v[2], k), u4(v[3], k), sel)) : "memory");
        }
        fence_async_smem();
    }
    __syncthreads();
    if (warp == 0 && elect_one()) {
        asm volatile("cp.async.bulk.tensor.3d.global.shared::cta.bulk_group [%0, {%2, %3, 0}], [%1];" ::"l"(TMAP(9)), "r"(sb + 2 * Q_SB), "r"(80 * hg), "r"(16 * blk) : "memory");
        bulk_commit();
        asm volatile("cp.async.bulk.wait_group.read 0;" ::: "memory");
    }
    if (bx == 0 && tid == 0) g_epoch = (EPOCH + 1) & 0x3FFFFFFFu;
    TS(22);
    TS_END;
}
typedef CUresult (*EncodeTiledFn)(CUtensorMap*, CUtensorMapDataType, cuuint32_t, void*, const cuuint64_t*, const cuuint64_t*, const cuuint32_t*,
                                  const cuuint32_t*, CUtensorMapInterleave, CUtensorMapSwizzle, CUtensorMapL2promotion, CUtensorMapFloatOOBfill);

static void make_map(EncodeTiledFn enc, CUtensorMap* m, const void* base, int rank, const cuuint64_t* dims, const cuuint64_t* strides,
                     const cuuint32_t* box, CUtensorMapSwizzle sw) {
    cuuint32_t es[4] = {1, 1, 1, 1};
    enc(m, CU_TENSOR_MAP_DATA_TYPE_BFLOAT16, rank, (void*)base, dims, strides, box, es, CU_TENSOR_MAP_INTERLEAVE_NONE, sw,
        sw == CU_TENSOR_MAP_SWIZZLE_128B ? CU_TENSOR_MAP_L2_PROMOTION_L2_128B : CU_TENSOR_MAP_L2_PROMOTION_NONE, CU_TENSOR_MAP_FLOAT_OOB_FILL_NONE);
}

template <typename... KArgs, typename... Args>
static void launch(void (*kern)(KArgs...), int grid, int block, int smem, int cluster, bool pdl, Args... args) {
    cudaLaunchConfig_t cfg = {};
    cfg.gridDim = dim3(grid); cfg.blockDim = dim3(block); cfg.dynamicSmemBytes = smem; cfg.stream = cudaStreamPerThread;
    cudaLaunchAttribute at[2];
    int n = 0;
    if (cluster > 1) { at[n].id = cudaLaunchAttributeClusterDimension; at[n].val.clusterDim.x = cluster; at[n].val.clusterDim.y = 1; at[n].val.clusterDim.z = 1; n++; }
    if (pdl) { at[n].id = cudaLaunchAttributeProgrammaticStreamSerialization; at[n].val.programmaticStreamSerializationAllowed = 1; n++; }
    cfg.attrs = at; cfg.numAttrs = n;
    cudaLaunchKernelEx(&cfg, kern, KArgs(args)...);
}

struct HostState {
    bool ready = false;
    const void* key[4] = {nullptr, nullptr, nullptr, nullptr};
    CUtensorMap mX[2], mRes[2], mW, mWr, mWo, mOut, mFin, mResA;
    bf16 *x1T, *x2T;
    unsigned* epoch;
};

extern "C" void kernel_launch(void* const* d_in, const int* in_sizes, int n_in, void* d_out, int out_size) {
    const bf16* x = (const bf16*)d_in[0];
    const bf16* wqkv = (const bf16*)d_in[1];
    const bf16* wo = (const bf16*)d_in[2];
    const bf16* lar = (const bf16*)d_in[4];
    const bf16* aim = (const bf16*)d_in[5];
    const bf16* cre = (const bf16*)d_in[6];
    const bf16* cim = (const bf16*)d_in[7];
    const bf16* logdt = (const bf16*)d_in[8];
    const bf16* dskip = (const bf16*)d_in[9];
    static HostState hs;
    if (!hs.ready || hs.key[0] != wqkv || hs.key[1] != wo || hs.key[2] != x || hs.key[3] != d_out) {
        void* fn = nullptr;
        cudaDriverEntryPointQueryResult qr;
        cudaGetDriverEntryPoint("cuTensorMapEncodeTiled", &fn, cudaEnableDefault, &qr);
        EncodeTiledFn enc = (EncodeTiledFn)fn;
        cudaGetSymbolAddress((void**)&hs.epoch, g_epoch);
        cudaGetSymbolAddress((void**)&hs.x1T, g_x1T);
        cudaGetSymbolAddress((void**)&hs.x2T, g_x2T);
        {
            cuuint64_t d[3] = {DM, SEQ / 2, 2}, s[2] = {DM * 4, DM * 2};
            cuuint32_t b[3] = {64, 64, 2}, ba[3] = {64, 64, 1}, br[3] = {16, 64, 1};
            make_map(enc, &hs.mX[0], x, 3, d, s, b, CU_TENSOR_MAP_SWIZZLE_128B);
            make_map(enc, &hs.mResA, x, 3, d, s, ba, CU_TENSOR_MAP_SWIZZLE_128B);
            make_map(enc, &hs.mRes[0], x, 3, d, s, br, CU_TENSOR_MAP_SWIZZLE_32B);
            cuuint64_t d2[3] = {SEQ / 2, DM, 2}, s2[2] = {XP * 2, SEQ};
            cuuint32_t b2[3] = {64, 80, 2};
            make_map(enc, &hs.mX[1], hs.x2T, 3, d2, s2, b, CU_TENSOR_MAP_SWIZZLE_128B);
            make_map(enc, &hs.mRes[1], hs.x2T, 3, d2, s2, b2, CU_TENSOR_MAP_SWIZZLE_128B);
            cuuint64_t d3[2] = {SEQ, DM};
            make_map(enc, &hs.mOut, hs.x1T, 2, d3, s2, b2, CU_TENSOR_MAP_SWIZZLE_128B);
        }
        { cuuint64_t d[2] = {3 * DM, DM}, s[1] = {3 * DM * 2}; cuuint32_t b[2] = {64, 32};
          make_map(enc, &hs.mW, wqkv, 2, d, s, b, CU_TENSOR_MAP_SWIZZLE_128B); }
        { cuuint64_t d[3] = {DM, DM, 3}, s[2] = {3 * DM * 2, DM * 2}; cuuint32_t b[3] = {16, 32, 3};
          make_map(enc, &hs.mWr, wqkv, 3, d, s, b, CU_TENSOR_MAP_SWIZZLE_32B); }
        { cuuint64_t d[4] = {8, 8, DM / 8, DM / 8}, s[3] = {DM * 2, 16, DM * 16}; cuuint32_t b[4] = {8, 8, 10, 5};
          make_map(enc, &hs.mWo, wo, 4, d, s, b, CU_TENSOR_MAP_SWIZZLE_NONE); }
        { cuuint64_t d[3] = {DM, SEQ / 8, 8}, s[2] = {DM * 16, DM * 2}; cuuint32_t b[3] = {80, 16, 8};
          make_map(enc, &hs.mFin, d_out, 3, d, s, b, CU_TENSOR_MAP_SWIZZLE_NONE); }
        cudaFuncSetAttribute(fused_kernel, cudaFuncAttributeMaxDynamicSharedMemorySize, Q_SMEM);
        hs.key[0] = wqkv; hs.key[1] = wo; hs.key[2] = x; hs.key[3] = d_out;
        hs.ready = true;
    }
    const SsmParams sp = {lar, aim, cre, cim, logdt, dskip, hs.epoch};
    launch(fused_kernel, 128, 384, Q_SMEM, 2, false, sp, hs.mX[0], hs.mX[1], hs.mW, hs.mWr, hs.mRes[0], hs.mRes[1], hs.mOut, hs.mWo, hs.mFin, hs.mResA);
}
```

```cpp
#include <cuda_runtime.h>
#include <cuda.h>
#include <cuda_bf16.h>
#include <cuda_fp16.h>
#include <stdint.h>

typedef __nv_bfloat16 bf16;

constexpr int SEQ = 2048;
constexpr int DM  = 640;
constexpr int XP  = SEQ + 64;
constexpr int NMODE = 192;

__device__ __forceinline__ uint32_t s2u(const void* p) { return (uint32_t)__cvta_generic_to_shared(p); }
__device__ __forceinline__ void mbar_init(uint32_t b, int c) { asm volatile("mbarrier.init.shared::cta.b64 [%0], %1;" ::"r"(b), "r"(c)); }
__device__ __forceinline__ void mbar_expect(uint32_t b, uint32_t bytes) { asm volatile("mbarrier.arrive.expect_tx.shared::cta.b64 _, [%0], %1;" ::"r"(b), "r"(bytes) : "memory"); }
__device__ __forceinline__ void mbar_arrive(uint32_t b) { asm volatile("mbarrier.arrive.shared::cta.b64 _, [%0];" ::"r"(b) : "memory"); }
__device__ __forceinline__ void mbar_arrive_cta(uint32_t b, uint32_t cta) {
    asm volatile("{\n.reg .b32 ra;\nmapa.shared::cluster.u32 ra, %0, %1;\nmbarrier.arrive.shared::cluster.b64 _, [ra];\n}" ::"r"(b), "r"(cta) : "memory");
}
__device__ __forceinline__ void mbar_wait(uint32_t b, uint32_t ph) {
#ifdef M_SAFE
    asm volatile("{\n.reg .pred p;\n.reg .u32 n;\nmbarrier.try_wait.parity.shared::cta.b64 p, [%0], %1;\n@p bra D;\nmov.u32 n, 0;\n"
                 "W: mbarrier.try_wait.parity.shared::cta.b64 p, [%0], %1;\n@p bra D;\nadd.u32 n, n, 1;\nsetp.lt.u32 p, n, 4194304;\n@p bra W;\ntrap;\nD:\n}"
                 ::"r"(b), "r"(ph) : "memory");
#else
    asm volatile("{\n.reg .pred p;\nW: mbarrier.try_wait.parity.shared::cta.b64 p, [%0], %1;\n@!p bra W;\n}" ::"r"(b), "r"(ph) : "memory");
#endif
}
__device__ __forceinline__ void fence_mbar_init() { asm volatile("fence.mbarrier_init.release.cluster;" ::: "memory"); }
__device__ __forceinline__ void cluster_sync() { asm volatile("barrier.cluster.arrive.aligned;\nbarrier.cluster.wait.aligned;" ::: "memory"); }
__device__ __forceinline__ void pdl_wait() { asm volatile("griddepcontrol.wait;" ::: "memory"); }
__device__ __forceinline__ void pdl_launch() { asm volatile("griddepcontrol.launch_dependents;" ::: "memory"); }
__device__ __forceinline__ void named_bar(int id, int n) { asm volatile("bar.sync %0, %1;" ::"r"(id), "r"(n) : "memory"); }
__device__ __forceinline__ void fence_async_smem() { asm volatile("fence.proxy.async.shared::cta;" ::: "memory"); }

__device__ __forceinline__ void tma2d(uint32_t dst, const CUtensorMap* m, int c0, int c1, uint32_t bar) {
    asm volatile("cp.async.bulk.tensor.2d.shared::cluster.global.mbarrier::complete_tx::bytes [%0], [%1, {%3, %4}], [%2];"
                 ::"r"(dst), "l"(m), "r"(bar), "r"(c0), "r"(c1) : "memory");
}
__device__ __forceinline__ void tma2d_mc(uint32_t dst, const CUtensorMap* m, int c0, int c1, uint32_t bar, uint16_t mask) {
    asm volatile("cp.async.bulk.tensor.2d.shared::cluster.global.mbarrier::complete_tx::bytes.multicast::cluster [%0], [%1, {%3, %4}], [%2], %5;"
                 ::"r"(dst), "l"(m), "r"(bar), "r"(c0), "r"(c1), "h"(mask) : "memory");
}
__device__ __forceinline__ void tma3d(uint32_t dst, const CUtensorMap* m, int c0, int c1, int c2, uint32_t bar) {
    asm volatile("cp.async.bulk.tensor.3d.shared::cluster.global.mbarrier::complete_tx::bytes [%0], [%1, {%3, %4, %5}], [%2];"
                 ::"r"(dst), "l"(m), "r"(bar), "r"(c0), "r"(c1), "r"(c2) : "memory");
}
__device__ __forceinline__ void tma3d_mc(uint32_t dst, const CUtensorMap* m, int c0, int c1, int c2, uint32_t bar, uint16_t mask) {
    asm volatile("cp.async.bulk.tensor.3d.shared::cluster.global.mbarrier::complete_tx::bytes.multicast::cluster [%0], [%1, {%3, %4, %5}], [%2], %6;"
                 ::"r"(dst), "l"(m), "r"(bar), "r"(c0), "r"(c1), "r"(c2), "h"(mask) : "memory");
}
__device__ __forceinline__ void bulk_g2s(uint32_t dst, const void* src, uint32_t bytes, uint32_t bar) {
    asm volatile("cp.async.bulk.shared::cluster.global.mbarrier::complete_tx::bytes [%0], [%1], %2, [%3];"
                 ::"r"(dst), "l"(src), "r"(bytes), "r"(bar) : "memory");
}
__device__ __forceinline__ void bulk_g2s_mc(uint32_t dst, const void* src, uint32_t bytes, uint32_t bar, uint16_t mask) {
    asm volatile("cp.async.bulk.shared::cluster.global.mbarrier::complete_tx::bytes.multicast::cluster [%0], [%1], %2, [%3], %4;"
                 ::"r"(dst), "l"(src), "r"(bytes), "r"(bar), "h"(mask) : "memory");
}
__device__ __forceinline__ void prefetch_l2(const void* p, uint32_t bytes) { asm volatile("cp.async.bulk.prefetch.L2.global [%0], %1;" ::"l"(p), "r"(bytes) : "memory"); }
__device__ __forceinline__ void prefetch_tmap(const CUtensorMap* m) { asm volatile("prefetch.tensormap [%0];" ::"l"(m) : "memory"); }

__device__ __forceinline__ void wg_fence() { asm volatile("wgmma.fence.sync.aligned;" ::: "memory"); }
__device__ __forceinline__ void wg_commit() { asm volatile("wgmma.commit_group.sync.aligned;" ::: "memory"); }
template <int N> __device__ __forceinline__ void wg_wait() { asm volatile("wgmma.wait_group.sync.aligned %0;" ::"n"(N) : "memory"); }
__device__ __forceinline__ uint64_t mkdesc(uint32_t addr, uint32_t lbo, uint32_t sbo, uint32_t mode) {
    return (uint64_t)((addr & 0x3FFFF) >> 4) | ((uint64_t)(lbo >> 4) << 16) | ((uint64_t)(sbo >> 4) << 32) | ((uint64_t)mode << 62);
}

__device__ __forceinline__ void mma16816(float (&c)[4], uint32_t a0, uint32_t a1, uint32_t a2, uint32_t a3, uint32_t b0, uint32_t b1) {
    asm("mma.sync.aligned.m16n8k16.row.col.f32.bf16.bf16.f32 {%0,%1,%2,%3},{%4,%5,%6,%7},{%8,%9},{%0,%1,%2,%3};"
                 : "+f"(c[0]), "+f"(c[1]), "+f"(c[2]), "+f"(c[3]) : "r"(a0), "r"(a1), "r"(a2), "r"(a3), "r"(b0), "r"(b1));
}
__device__ __forceinline__ void mma1688(float (&c)[4], uint32_t a0, uint32_t a1, uint32_t b0) {
    asm("mma.sync.aligned.m16n8k8.row.col.f32.bf16.bf16.f32 {%0,%1,%2,%3},{%4,%5},{%6},{%0,%1,%2,%3};"
                 : "+f"(c[0]), "+f"(c[1]), "+f"(c[2]), "+f"(c[3]) : "r"(a0), "r"(a1), "r"(b0));
}
__device__ __forceinline__ void ldsm_x4(uint32_t& r0, uint32_t& r1, uint32_t& r2, uint32_t& r3, uint32_t a) {
    asm volatile("ldmatrix.sync.aligned.m8n8.x4.shared.b16 {%0,%1,%2,%3}, [%4];" : "=r"(r0), "=r"(r1), "=r"(r2), "=r"(r3) : "r"(a) : "memory");
}
__device__ __forceinline__ void ldsm_x4_t(uint32_t& r0, uint32_t& r1, uint32_t& r2, uint32_t& r3, uint32_t a) {
    asm volatile("ldmatrix.sync.aligned.m8n8.x4.trans.shared.b16 {%0,%1,%2,%3}, [%4];" : "=r"(r0), "=r"(r1), "=r"(r2), "=r"(r3) : "r"(a) : "memory");
}
__device__ __forceinline__ void ldsm_x2(uint32_t& r0, uint32_t& r1, uint32_t a) {
    asm volatile("ldmatrix.sync.aligned.m8n8.x2.shared.b16 {%0,%1}, [%2];" : "=r"(r0), "=r"(r1) : "r"(a) : "memory");
}
__device__ __forceinline__ void ldsm_x2_t(uint32_t& r0, uint32_t& r1, uint32_t a) {
    asm volatile("ldmatrix.sync.aligned.m8n8.x2.trans.shared.b16 {%0,%1}, [%2];" : "=r"(r0), "=r"(r1) : "r"(a) : "memory");
}
__device__ __forceinline__ void stsm_x4(uint32_t a, uint32_t r0, uint32_t r1, uint32_t r2, uint32_t r3) {
    asm volatile("stmatrix.sync.aligned.m8n8.x4.shared.b16 [%0], {%1,%2,%3,%4};" ::"r"(a), "r"(r0), "r"(r1), "r"(r2), "r"(r3) : "memory");
}
__device__ __forceinline__ void stsm_x4_t(uint32_t a, uint32_t r0, uint32_t r1, uint32_t r2, uint32_t r3) {
    asm volatile("stmatrix.sync.aligned.m8n8.x4.trans.shared.b16 [%0], {%1,%2,%3,%4};" ::"r"(a), "r"(r0), "r"(r1), "r"(r2), "r"(r3) : "memory");
}
__device__ __forceinline__ void stsm_x2(uint32_t a, uint32_t r0, uint32_t r1) {
    asm volatile("stmatrix.sync.aligned.m8n8.x2.shared.b16 [%0], {%1,%2};" ::"r"(a), "r"(r0), "r"(r1) : "memory");
}
__device__ __forceinline__ uint32_t movm_t(uint32_t a) {
    uint32_t d;
    asm volatile("movmatrix.sync.aligned.m8n8.trans.b16 %0, %1;" : "=r"(d) : "r"(a));
    return d;
}
__device__ __forceinline__ uint32_t lds32(uint32_t a) { uint32_t v; asm volatile("ld.shared.u32 %0, [%1];" : "=r"(v) : "r"(a) : "memory"); return v; }
__device__ __forceinline__ uint32_t ldsv32(uint32_t a) { uint32_t v; asm volatile("ld.volatile.shared.u32 %0, [%1];" : "=r"(v) : "r"(a) : "memory"); return v; }
__device__ __forceinline__ void sts32(uint32_t a, uint32_t v) { asm volatile("st.shared.u32 [%0], %1;" ::"r"(a), "r"(v) : "memory"); }
__device__ __forceinline__ uint4 lds128(uint32_t a) { uint4 v; asm volatile("ld.shared.v4.u32 {%0,%1,%2,%3}, [%4];" : "=r"(v.x), "=r"(v.y), "=r"(v.z), "=r"(v.w) : "r"(a) : "memory"); return v; }
__device__ __forceinline__ void sts128(uint32_t a, uint4 v) { asm volatile("st.shared.v4.u32 [%0], {%1,%2,%3,%4};" ::"r"(a), "r"(v.x), "r"(v.y), "r"(v.z), "r"(v.w) : "memory"); }

__device__ __forceinline__ void stg128(void* p, uint4 v) { asm volatile("st.global.v4.u32 [%0], {%1,%2,%3,%4};" ::"l"(p), "r"(v.x), "r"(v.y), "r"(v.z), "r"(v.w) : "memory"); }

__device__ __forceinline__ uint4 ldg128(const void* p) { uint4 v; asm volatile("ld.global.v4.u32 {%0,%1,%2,%3}, [%4];" : "=r"(v.x), "=r"(v.y), "=r"(v.z), "=r"(v.w) : "l"(p) : "memory"); return v; }
__device__ __forceinline__ uint2 ldg64(const void* p) { uint2 v; asm volatile("ld.global.v2.u32 {%0,%1}, [%2];" : "=r"(v.x), "=r"(v.y) : "l"(p) : "memory"); return v; }
__device__ __forceinline__ uint32_t ldg32(const void* p) { uint32_t v; asm volatile("ld.global.u32 %0, [%1];" : "=r"(v) : "l"(p) : "memory"); return v; }

__device__ __forceinline__ uint32_t pack2(float lo, float hi) {
    uint32_t r;
    asm("cvt.rn.bf16x2.f32 %0, %1, %2;" : "=r"(r) : "f"(hi), "f"(lo));
    return r;
}
__device__ __forceinline__ float bf_lo(uint32_t v) { return __uint_as_float(v << 16); }
__device__ __forceinline__ float bf_hi(uint32_t v) { return __uint_as_float(v & 0xFFFF0000u); }
__device__ __forceinline__ float rbf(float x) { return __uint_as_float(pack2(0.f, x) & 0xFFFF0000u); }
__device__ __forceinline__ float ex2(float x) { float r; asm("ex2.approx.ftz.f32 %0, %1;" : "=f"(r) : "f"(x)); return r; }

__device__ __forceinline__ float2 ln_finish(float sum, float sumsq) {
    const float m = sum * (1.0f / DM);
    const float v = fmaxf(fmaf(sumsq, 1.0f / DM, -m * m), 0.f);
    float s, r;
    asm("sqrt.approx.ftz.f32 %0, %1;" : "=f"(s) : "f"(rbf(rbf(v) + 1e-5f)));
    asm("rcp.approx.ftz.f32 %0, %1;" : "=f"(r) : "f"(rbf(s)));
    return make_float2(m, r);
}
__device__ __forceinline__ uint32_t ln_finish_packed(float sum, float sumsq) {
    const float m = sum * (1.0f / DM);
    const float v = fmaxf(fmaf(sumsq, 1.0f / DM, -m * m), 0.f);
    float s;
    asm("sqrt.approx.ftz.f32 %0, %1;" : "=f"(s) : "f"(rbf(rbf(v) + 1e-5f)));
    return pack2(s, m);
}
__device__ __forceinline__ float frsq(float x) { float r; asm("rsqrt.approx.ftz.f32 %0, %1;" : "=f"(r) : "f"(x)); return r; }
__device__ __forceinline__ float frcp(float x) { float r; asm("rcp.approx.ftz.f32 %0, %1;" : "=f"(r) : "f"(x)); return r; }
__device__ __forceinline__ bool elect_one() {
    uint32_t p;
    asm volatile("{\n.reg .pred p;\nelect.sync _|p, 0xffffffff;\nselp.u32 %0, 1, 0, p;\n}" : "=r"(p));
    return p != 0;
}
__device__ __forceinline__ void cluster_arrive_relaxed() { asm volatile("barrier.cluster.arrive.relaxed.aligned;" ::: "memory"); }
__device__ __forceinline__ void cluster_wait() { asm volatile("barrier.cluster.wait.aligned;" ::: "memory"); }
__device__ __forceinline__ unsigned long long ld_ll(const unsigned long long* p) {
    unsigned long long v;
    asm volatile("ld.relaxed.gpu.global.b64 %0, [%1];" : "=l"(v) : "l"(p) : "memory");
    return v;
}
__device__ __forceinline__ void st_ll(unsigned long long* p, uint32_t payload, uint32_t tag) {
    const unsigned long long v = (unsigned long long)payload | ((unsigned long long)tag << 32);
    asm volatile("st.relaxed.gpu.global.b64 [%0], %1;" ::"l"(p), "l"(v) : "memory");
}
__device__ __forceinline__ uint4 ld_ll4(const uint4* p) {
    uint4 v;
    asm volatile("{\n.reg .b128 t;\n.reg .b64 a, b;\nld.relaxed.gpu.global.b128 t, [%4];\nmov.b128 {a, b}, t;\nmov.b64 {%0, %1}, a;\nmov.b64 {%2, %3}, b;\n}"
                 : "=r"(v.x), "=r"(v.y), "=r"(v.z), "=r"(v.w) : "l"(p) : "memory");
    return v;
}
__device__ __forceinline__ void st_ll4(uint4* p, uint32_t x, uint32_t y, uint32_t z, uint32_t w) {
    asm volatile("{\n.reg .b128 t;\n.reg .b64 a, b;\nmov.b64 a, {%1, %2};\nmov.b64 b, {%3, %4};\nmov.b128 t, {a, b};\nst.relaxed.gpu.global.b128 [%0], t;\n}"
                 ::"l"(p), "r"(x), "r"(y), "r"(z), "r"(w) : "memory");
}

__device__ __forceinline__ void bulk_s2g(void* dst, uint32_t src, uint32_t bytes) {
    asm volatile("cp.async.bulk.global.shared::cta.bulk_group [%0], [%1], %2;" ::"l"(dst), "r"(src), "r"(bytes) : "memory");
}
__device__ __forceinline__ void bulk_commit() { asm volatile("cp.async.bulk.commit_group;" ::: "memory"); }
__device__ __forceinline__ void bulk_wait() { asm volatile("cp.async.bulk.wait_group 0;" ::: "memory"); }
__device__ __forceinline__ void fence_async_global() { asm volatile("fence.proxy.async.global;" ::: "memory"); }
__device__ __forceinline__ void fence_release() { asm volatile("fence.release.gpu;" ::: "memory"); }
__device__ __forceinline__ void fence_acquire() { asm volatile("fence.acquire.gpu;" ::: "memory"); }
__device__ __forceinline__ void ll_check5(uint4 (&f)[5], const uint4* p, uint32_t mark) {
#define LL_LD(i, a, b, c, d) "ld.relaxed.gpu.global.b128 q, [%20 + " #i "];\nmov.b128 {u, v}, q;\nmov.b64 {%" #a ", %" #b "}, u;\nmov.b64 {%" #c ", %" #d "}, v;\n"
    asm volatile("{\n.reg .pred p;\n.reg .b32 t, n, m;\n.reg .b128 q;\n.reg .b64 u, v;\nmov.u32 n, 0x7FFFF;\n"
                 "L:\nlop3.b32 t, %0, %4, %21, 0x7E;\nlop3.b32 t, t, %8, %21, 0xF6;\nlop3.b32 t, t, %12, %21, 0xF6;\nlop3.b32 t, t, %16, %21, 0xF6;\n"
                 "shr.u32 m, n, 18;\nand.b32 t, t, m;\nsetp.ne.u32 p, t, 0;\nvote.sync.any.pred p, p, 0xffffffff;\n@!p bra.uni D;\n"
                 LL_LD(0, 0, 1, 2, 3) LL_LD(512, 4, 5, 6, 7) LL_LD(1024, 8, 9, 10, 11) LL_LD(1536, 12, 13, 14, 15) LL_LD(2048, 16, 17, 18, 19)
                 "sub.u32 n, n, 1;\nbra.uni L;\nD:\n}"
                 : "+r"(f[0].x), "+r"(f[0].y), "+r"(f[0].z), "+r"(f[0].w), "+r"(f[1].x), "+r"(f[1].y), "+r"(f[1].z), "+r"(f[1].w), "+r"(f[2].x), "+r"(f[2].y),
                   "+r"(f[2].z), "+r"(f[2].w), "+r"(f[3].x), "+r"(f[3].y), "+r"(f[3].z), "+r"(f[3].w), "+r"(f[4].x), "+r"(f[4].y), "+r"(f[4].z), "+r"(f[4].w)
                 : "l"(p), "r"(mark) : "memory");
}
template<int TA, int TB>
__device__ __forceinline__ void wgmma_n192(float (&d)[96], uint64_t da, uint64_t db, int scale_d) {
  asm volatile("{\n.reg .pred p;\nsetp.ne.b32 p, %98, 0;\n"
    "wgmma.mma_async.sync.aligned.m64n192k16.f32.bf16.bf16 "
    "{%0, %1, %2, %3, %4, %5, %6, %7, %8, %9, %10, %11, %12, %13, %14, %15, %16, %17, %18, %19, %20, %21, %22, %23, %24, %25, %26, %27, %28, %29, %30, %31, %32, %33, %34, %35, %36, %37, %38, %39, %40, %41, %42, %43, %44, %45, %46, %47, %48, %49, %50, %51, %52, %53, %54, %55, %56, %57, %58, %59, %60, %61, %62, %63, %64, %65, %66, %67, %68, %69, %70, %71, %72, %73, %74, %75, %76, %77, %78, %79, %80, %81, %82, %83, %84, %85, %86, %87, %88, %89, %90, %91, %92, %93, %94, %95}, %96, %97, p, 1, 1, %99, %100;\n}\n"
    : "+f"(d[0]), "+f"(d[1]), "+f"(d[2]), "+f"(d[3]), "+f"(d[4]), "+f"(d[5]), "+f"(d[6]), "+f"(d[7]), "+f"(d[8]), "+f"(d[9]), "+f"(d[10]), "+f"(d[11]), "+f"(d[12]), "+f"(d[13]), "+f"(d[14]), "+f"(d[15]), "+f"(d[16]), "+f"(d[17]), "+f"(d[18]), "+f"(d[19]), "+f"(d[20]), "+f"(d[21]), "+f"(d[22]), "+f"(d[23]), "+f"(d[24]), "+f"(d[25]), "+f"(d[26]), "+f"(d[27]), "+f"(d[28]), "+f"(d[29]), "+f"(d[30]), "+f"(d[31]), "+f"(d[32]), "+f"(d[33]), "+f"(d[34]), "+f"(d[35]), "+f"(d[36]), "+f"(d[37]), "+f"(d[38]), "+f"(d[39]), "+f"(d[40]), "+f"(d[41]), "+f"(d[42]), "+f"(d[43]), "+f"(d[44]), "+f"(d[45]), "+f"(d[46]), "+f"(d[47]), "+f"(d[48]), "+f"(d[49]), "+f"(d[50]), "+f"(d[51]), "+f"(d[52]), "+f"(d[53]), "+f"(d[54]), "+f"(d[55]), "+f"(d[56]), "+f"(d[57]), "+f"(d[58]), "+f"(d[59]), "+f"(d[60]), "+f"(d[61]), "+f"(d[62]), "+f"(d[63]), "+f"(d[64]), "+f"(d[65]), "+f"(d[66]), "+f"(d[67]), "+f"(d[68]), "+f"(d[69]), "+f"(d[70]), "+f"(d[71]), "+f"(d[72]), "+f"(d[73]), "+f"(d[74]), "+f"(d[75]), "+f"(d[76]), "+f"(d[77]), "+f"(d[78]), "+f"(d[79]), "+f"(d[80]), "+f"(d[81]), "+f"(d[82]), "+f"(d[83]), "+f"(d[84]), "+f"(d[85]), "+f"(d[86]), "+f"(d[87]), "+f"(d[88]), "+f"(d[89]), "+f"(d[90]), "+f"(d[91]), "+f"(d[92]), "+f"(d[93]), "+f"(d[94]), "+f"(d[95])
    : "l"(da), "l"(db), "r"(scale_d), "n"(TA), "n"(TB));
}

template<int TA, int TB>
__device__ __forceinline__ void wgmma_n48(float (&d)[24], uint64_t da, uint64_t db, int scale_d) {
  asm volatile("{\n.reg .pred p;\nsetp.ne.b32 p, %26, 0;\n"
    "wgmma.mma_async.sync.aligned.m64n48k16.f32.bf16.bf16 "
    "{%0, %1, %2, %3, %4, %5, %6, %7, %8, %9, %10, %11, %12, %13, %14, %15, %16, %17, %18, %19, %20, %21, %22, %23}, %24, %25, p, 1, 1, %27, %28;\n}\n"
    : "+f"(d[0]), "+f"(d[1]), "+f"(d[2]), "+f"(d[3]), "+f"(d[4]), "+f"(d[5]), "+f"(d[6]), "+f"(d[7]), "+f"(d[8]), "+f"(d[9]), "+f"(d[10]), "+f"(d[11]), "+f"(d[12]), "+f"(d[13]), "+f"(d[14]), "+f"(d[15]), "+f"(d[16]), "+f"(d[17]), "+f"(d[18]), "+f"(d[19]), "+f"(d[20]), "+f"(d[21]), "+f"(d[22]), "+f"(d[23])
    : "l"(da), "l"(db), "r"(scale_d), "n"(TA), "n"(TB));
}

__device__ __forceinline__ void wgmma_rs80(float (&d)[40], const uint4& a, uint64_t db, int scale_d) {
  asm volatile("{\n.reg .pred p;\nsetp.ne.b32 p, %45, 0;\n"
    "wgmma.mma_async.sync.aligned.m64n80k16.f32.bf16.bf16 {%0,%1,%2,%3,%4,%5,%6,%7,%8,%9,%10,%11,%12,%13,%14,%15,%16,%17,%18,%19,%20,%21,%22,%23,%24,%25,%26,%27,%28,%29,%30,%31,%32,%33,%34,%35,%36,%37,%38,%39}, {%40,%41,%42,%43}, %44, p, 1, 1, 1;\n}\n"
    : "+f"(d[0]), "+f"(d[1]), "+f"(d[2]), "+f"(d[3]), "+f"(d[4]), "+f"(d[5]), "+f"(d[6]), "+f"(d[7]), "+f"(d[8]), "+f"(d[9]), "+f"(d[10]), "+f"(d[11]), "+f"(d[12]), "+f"(d[13]), "+f"(d[14]), "+f"(d[15]), "+f"(d[16]), "+f"(d[17]), "+f"(d[18]), "+f"(d[19]), "+f"(d[20]), "+f"(d[21]), "+f"(d[22]), "+f"(d[23]), "+f"(d[24]), "+f"(d[25]), "+f"(d[26]), "+f"(d[27]), "+f"(d[28]), "+f"(d[29]), "+f"(d[30]), "+f"(d[31]), "+f"(d[32]), "+f"(d[33]), "+f"(d[34]), "+f"(d[35]), "+f"(d[36]), "+f"(d[37]), "+f"(d[38]), "+f"(d[39])
    : "r"(a.x), "r"(a.y), "r"(a.z), "r"(a.w), "l"(db), "r"(scale_d));
}

__device__ __forceinline__ void wgmma_ss80(float (&d)[40], uint64_t da, uint64_t db) {
  asm volatile("wgmma.mma_async.sync.aligned.m64n80k16.f32.bf16.bf16 {%0,%1,%2,%3,%4,%5,%6,%7,%8,%9,%10,%11,%12,%13,%14,%15,%16,%17,%18,%19,%20,%21,%22,%23,%24,%25,%26,%27,%28,%29,%30,%31,%32,%33,%34,%35,%36,%37,%38,%39}, %40, %41, 1, 1, 1, 0, 1;"
    : "+f"(d[0]), "+f"(d[1]), "+f"(d[2]), "+f"(d[3]), "+f"(d[4]), "+f"(d[5]), "+f"(d[6]), "+f"(d[7]), "+f"(d[8]), "+f"(d[9]), "+f"(d[10]), "+f"(d[11]), "+f"(d[12]), "+f"(d[13]), "+f"(d[14]), "+f"(d[15]), "+f"(d[16]), "+f"(d[17]), "+f"(d[18]), "+f"(d[19]), "+f"(d[20]), "+f"(d[21]), "+f"(d[22]), "+f"(d[23]), "+f"(d[24]), "+f"(d[25]), "+f"(d[26]), "+f"(d[27]), "+f"(d[28]), "+f"(d[29]), "+f"(d[30]), "+f"(d[31]), "+f"(d[32]), "+f"(d[33]), "+f"(d[34]), "+f"(d[35]), "+f"(d[36]), "+f"(d[37]), "+f"(d[38]), "+f"(d[39])
    : "l"(da), "l"(db));
}

__device__ const __align__(1024) uint32_t c_fft[11264] = {
0x2ddc2dba,0x2fe62eb5,0x2ed02eb5,0xafffaf6e,0x2e1f2dfe,0x2e3f2fbc,0x2f022ee9,0xad27af30,0x2e5e2e3f,0x1fd92b5e,0x2f302f1a,0x244ea875,0x2e992e7c,0xad96a993,0x2f5a2f46,0x2e992c32,
0xad00ad72,0xa17eac32,0xa17ea515,0xabb79cb6,0xac07ac87,0x2dfe29f1,0x1fd99648,0xafedae99,0xa9f1ab05,0x2fd42fbc,0x26a1244e,0xad96af91,0xa765a8d5,0x2aaa2e3f,0x29932875,0x2515a8d5,
0xae99adfe,0xb000aee9,0xaf6eafbc,0x2c872f30,0xaf80af1a,0xac32af02,0xae7caf02,0xaaaa217e,0xaff4afc9,0x2b5e9cb6,0xad27addc,0xaff4ae7c,0xafedb000,0x2ffc2eb5,0xab05ac5d,0xacd8af5a,
0x2c072d27,0x9fd92bb7,0xadfead00,0x2fed2e1f,0x25db2993,0xaf6eacb0,0xaf6eaed0,0x2c5d2f46,0xa5151648,0xaddcafdd,0xafffafd4,0xac321648,0xabb7a934,0x28d5a814,0xafa0afed,0xaff4af30,
0x2f302e3f,0x2fed2f1a,0x28142b5e,0x2934a875,0x30002fc9,0x26a12ddc,0xa5db1cb6,0x30002e7c,0x2f462fd4,0xaed0aa4e,0xacb0aa4e,0x29932e99,0x2d272e5e,0xae3faffc,0xaf02adfe,0xae1fa814,
0xa9f1acd8,0x26a1ab05,0x2fd42ffc,0xad96afed,0x2515a30e,0x2fff2e1f,0x2ddc2f1a,0x2c32a30e,0x2d272aaa,0x28752e7c,0x28752c32,0x2fa02f80,0x2f912e99,0xaee9a9f1,0xa8141648,0x9fd92c87,
0xafa0ae7c,0xafafaf46,0x2d002993,0xafa0ac32,0xaf91b000,0x244eac5d,0x2fbc2eb5,0xab05af5a,0xac87ae5e,0x30002dfe,0x2f6e2ffc,0x2e992814,0x1cb6a875,0x25152e1f,0x2c322e1f,0x2d722ff4,
0x27652c87,0xa9932a4e,0xaaaaadba,0xa5152c87,0xabb7a44e,0xafa0af30,0x28d59fd9,0xaff4ae5e,0xaf91ae1f,0x2814abb7,0x2ee92d00,0x1fd9ad27,0xaf5aafff,0x2fd42ed0,0x2fd42fe6,0x30002ddc,
0x2f462f6e,0x2c322fdd,0x2e7c2fdd,0xa993b000,0xab5e2934,0xafafacd8,0xad00244e,0x2f1a2dfe,0xaee9afaf,0x2f30a17e,0xadfeaff8,0xafbca30e,0x2c5da765,0xa9f12ddc,0x2d969cb6,0x2c5dacb0,
0x2bb7a993,0x2f1aa515,0x2f1a2765,0xaff4aaaa,0x2e5e2fd4,0xab052dba,0x29342f6e,0x2ee9a6a1,0xadba1fd9,0xa5dbafed,0xafddac07,0xaa4e2dfe,0xacb0aff8,0x2ddc2f02,0x9cb6ae3f,0xa765aff8,
0xaeb5af91,0xaa4eafed,0x9648ae5e,0xac5d2d4d,0x2ddca17e,0x2e7c2e3f,0x2fc92e3f,0x1cb6afa0,0x2bb72fe6,0xaff8a993,0xab5e2aaa,0x2bb72fc9,0xafbcaa4e,0x2f30a5db,0xadfeafdd,0xaee9adba,
0xacd828d5,0xaf91230e,0xaf30af02,0x2c072fa0,0xac5dafff,0x2dbaac32,0x2dbaa515,0xae99addc,0x2fc929f1,0xa9932eb5,0x2aaa2fdd,0x2fe629f1,0xa30e2dfe,0xa17eafed,0xaff8ac07,0xafaf1fd9,
0x2dfe2faf,0x28142ff8,0xae5e217e,0x2ffc230e,0xaf5aa515,0xac87af46,0xa6a1af80,0xaf5a2765,0x1cb6ae99,0x2e7c2dba,0x2fc92dba,0x2ddcac5d,0x2f1a2ee9,0xafafab05,0xad002934,0xab5e2e5e,
0x2dbaa814,0x2fdd9fd9,0x25db2f91,0x2a4eaee9,0x27652faf,0xaf4628d5,0xaf80ae1f,0xa5152faf,0xafa0addc,0x2e3fac32,0x2e3fa515,0xa17eafff,0x2dfea6a1,0xacd82dba,0x244e2f6e,0x29342fd4,
0xad27afc9,0xa30eafff,0x2faf2d72,0xad27ae7c,0x2ffc2a4e,0x28142fdd,0xae5e25db,0x2dfe2dba,0xac5d2c07,0xaa4eaf91,0x9648af30,0xaeb5acd8,0xa993aff4,0x2c322f1a,0x2e7c2f1a,0x2f462bb7,
0xae7c26a1,0xafff1648,0x2d72aa4e,0xafc926a1,0x230eaee9,0x2ff89fd9,0x217e2f91,0x2fafa814,0x2d4d2fa0,0xafed230e,0xae5eaf02,0xaf9128d5,0xb000aaaa,0x2fdda515,0x2fdd2765,0x2f6ea993,
0x9cb63000,0xacb02fd4,0xa7652fd4,0x2ddcaf5a,0x217eaffc,0x2ff4ac07,0x2875afbc,0xaff82934,0xa44e2ff4,0xadfea8d5,0xa9342fa0,0x2cd82bb7,0x25dbafe6,0x16482f46,0x29f1af80,0x25dbafc9,
0x2ff41cb6,0x2e1f2765,0x2e1f2cb0,0xa875addc,0xafbca5db,0x1fd9af5a,0xad4dad96,0xacd82fdd,0x2f5a2934,0xaeb52ee9,0x2c5d2e5e,0x3000ab05,0xaed0ab5e,0x2f80a30e,0xaaaaaf02,0xacb0ab5e,
0x25dbaffc,0x2d96afbc,0x2f5aac07,0xafdd2934,0xaaaa2fa0,0xafc92875,0xafe62875,0x29932d27,0x2d00aed0,0x28d52d72,0x2ff89cb6,0x2d00afe6,0xae5e2d96,0x2d4dafd4,0xaf91a6a1,0xafed29f1,
0xafbca17e,0xad4da875,0x1fd9aff4,0xacd82ff8,0x2e992aaa,0xaa4e2fe6,0xaa4e2fc9,0x2fd4a993,0xacb0ad96,0x2fffac87,0x2d72aeb5,0xa765ad96,0x28752f30,0xab5eac07,0xaf1a2cd8,0xae3f2f91,
0xa9342ff4,0xae5e2fa0,0xaee9a8d5,0x2b052bb7,0x2d96aed0,0x2eb59cb6,0x2c872d72,0x2d96afe6,0xaf802c5d,0x2765af6e,0xa515af6e,0xaf4625db,0x2ff8a44e,0xaff42d4d,0xa8752ffc,0xa17e2ee9,
0x2f5a244e,0x2c5d2934,0xaeb52dfe,0x3000acd8,0xacb0ad00,0x2d72aff8,0x2fffa8d5,0xa765ad00,0x217e2f80,0xaf022515,0xaf02a765,0xaf1a2f46,0x2b05afdd,0xa8142f5a,0x2c072d96,0x2d4d25db,
0x2b5eafe6,0x2f02af80,0x230e2f46,0x2b5eafc9,0xaf302d96,0xacd8a6a1,0x2c07afd4,0xaf9129f1,0x2fdda44e,0xad962ffc,0xaf5a2d4d,0xa5db2ee9,0xad72abb7,0x2e7ca17e,0x2fc9a17e,0x2fffad00,
0xaed0a5db,0xaaaaa9f1,0x2f809648,0xacb0a5db,0x28752e5e,0xaf1a2f91,0xab5ead4d,0xae3f2fed,0x2b05aff8,0x2c072875,0xa8142ff4,0x2d4d217e,0xaf6e2d72,0x2eb5afc9,0x2eb5ae7c,0x2dbaafff,
0xaf802f5a,0xafc92e99,0xafe62e99,0x2f46ad96,0x28d52b05,0xaf022fed,0x230e2cd8,0x2fa0affc,0x2fbcaf02,0xa9342d27,0x2ffcae1f,0x2c07ae3f,0xa6a1ac32,0x2a4e9cb6,0x9648ad72,0xa6a1a515,
0x28752aaa,0xa8d52cb0,0xa8d52ed0,0x2e3faf80,0x2fedaeb5,0x29349648,0x2f30aa4e,0x2814ac5d,0x1648ad4d,0x2e99acd8,0x2c87afbc,0xa9f11fd9,0xafe62d27,0x2fffafaf,0xaddc230e,0xaed02d27,
0x2fd4af30,0x2f6eae5e,0x2dbaa44e,0xa6a19fd9,0x1cb6ad27,0x2fe6aff4,0x2ed0aff4,0xad722b5e,0xafaf2cb0,0x2e1faf46,0xa8d5a993,0xafaf2ed0,0xac072f6e,0x2934ac87,0xaffc2e99,0xafbc3000,
0xa44eab5e,0x2b05ad00,0x2f91afaf,0xafbc2f1a,0xafd42d72,0x1648a765,0x1648acb0,0xafdd2fff,0xac322f5a,0xaaaa26a1,0xaf802c87,0xae7c2f5a,0x2d009fd9,0xae1f2cd8,0xad272fbc,0xabb72d4d,
0xaffc2f02,0xaee92e1f,0x244ead27,0xad4d2e3f,0xa9f12e7c,0xafdd2f80,0xaeb52aaa,0xa9f12c32,0x2d72a5db,0xafe63000,0xaed03000,0x9cb626a1,0x2fa0afbc,0xaf022f91,0x230e2b05,0x28d5a44e,
0x96482c07,0xac872d4d,0xae992b05,0x29f1a814,0x2ed0abb7,0xa9932b5e,0xaf462ff8,0x2cb0abb7,0x2f1aafff,0xa30e2765,0xa30e2cb0,0x2e1fad72,0x1fd9ac5d,0x244e9648,0x2e5eaa4e,0x2f30aeb5,
0x2ff8aed0,0x2e3faddc,0xaf022fff,0x2ff8afe6,0x2d4daf6e,0x2ee9ae99,0xa44e2c87,0x2ffcb000,0xa6a1a814,0x2f6eaf30,0x2dbaa934,0x2fd4afed,0xaf462d00,0x2fc9afa0,0x2fe6afa0,0x2f80afaf,
0x2515ac5d,0x2d72ad96,0x1cb629f1,0x2c32ac5d,0xad002814,0x2d27ad4d,0x2e1fab05,0x2bb7ac07,0xaffc2f1a,0x2cd8ad00,0x2fedafaf,0x2b05ab5e,0xadba2f80,0x2c87acb0,0x2c87aed0,0x2a4eaaaa,
0x2f802f6e,0x2fc92fdd,0x2fe62fdd,0xaf46b000,0x2fa02f91,0x2bb72e5e,0x2ff42fed,0xa8d5ad4d,0x2fbc2faf,0xa934217e,0x2ffc2ff8,0x2c07230e,0x2fd42fc9,0xaf5aad72,0x30002fff,0x2fd42e7c,
0x2bb72aaa,0x2f1a2cb0,0x2f1a2ed0,0xaff4af80,0x2cd82c5d,0x2f303000,0x2f912f5a,0xac07aeb5,0x2dba2d4d,0x25db2cd8,0x2fdd2fbc,0x2a4e9fd9,0x2e7c2e1f,0xad72a875,0x2fff2ff4,0x2fc92e1f,
0xa6a1a934,0x29f1a44e,0x2d962cd8,0xafd4adfe,0x1cb6a17e,0x2fe62e3f,0x2ed02e3f,0xad72afa0,0x28752515,0x2d272f80,0x2fa02f46,0x2875a765,0x2c072a4e,0xa93425db,0x2ffc2fdd,0x2fbc2dba,
0xae5eaf1a,0xa934ae3f,0x2b052875,0xaee9ab5e,0xac5dad72,0x2dba2765,0x2dba2cb0,0xae99afff,0xa765aa4e,0x2f802fd4,0x2f462e99,0x2515aa4e,0x230e9fd9,0x217e2cd8,0x2ff82fbc,0x2faf2d4d,
0xaffcafaf,0xaee9aff8,0x244ea17e,0xad4da30e,0xaf6eafe6,0x25dbaaaa,0x2c5d2993,0xaf6eafc9,0xad72ae99,0x2fe62dba,0x2ed02dba,0x1cb6ac5d,0xa8d5ac07,0x2bb72f30,0x2ff42f91,0x2fa02cd8,
0xadbaac07,0xafddad4d,0xa5dbab05,0xaa4e2814,0xafc9af02,0xaaaaaf1a,0x2993217e,0xafe6af02,0xafa0afff,0x2e3f2765,0x2e3f2cb0,0xa17ead72,0xad4daeb5,0x2e5e3000,0x2fed2f5a,0x2f912c5d,
0xa17e2765,0xad001cb6,0xabb7addc,0xa17e2cb0,0xad4daa4e,0xaee9afdd,0x244ea5db,0xaffcadba,0xafd4aee9,0x29f1a934,0x2d962b05,0xa6a1ae5e,0xaf46aff4,0x2fc92f1a,0x2fe62f1a,0x2f802bb7,
0x2cb02eb5,0x1cb62dba,0xaddcaf6e,0x27652eb5,0xa30e2814,0xaff8ad4d,0xa17eab05,0xafafac07,0xadfeab5e,0xa44eae3f,0x2cd82875,0xa934af1a,0xb000af80,0x2fdd2cb0,0x2fdd2ed0,0x2f6e2aaa,
0x2d723000,0x25152fd4,0x2c322fd4,0x1cb6af5a,0xae1f9fd9,0xae3faee9,0xaf02a814,0x2d272f91,0xacd8aff4,0x2ffc28d5,0xab05afa0,0xafedabb7,0x2e992515,0xad962aaa,0x2f5a2993,0x2e99a765,
0x2ff42ddc,0x2e1f2ed0,0x2e1f2fe6,0xa875afff,0xa8142c87,0xaffca9f1,0xadfe1648,0x2e5e2e99,0xaf5aaf30,0x2eb5a814,0xac5dafed,0xb000a934,0x2c32a8d5,0xa9932e3f,0x2f462875,0x2e7ca8d5,
0x2e991fd9,0x30002814,0x2f6e2ee9,0xac87af91,0x29932fa0,0xaed02875,0xacb02875,0x2f462d27,0xaff4ac32,0x2b5eaddc,0xad27afff,0xaff4a515,0x244ead96,0x1fd92fd4,0x2f3026a1,0x2e5ea9f1,
0x2814ad27,0x2dfeabb7,0x2ffc2d00,0xae5eae1f,0x2e992f80,0xaa4e2e7c,0xaa4e2c32,0x2fd42aaa,0xae7c1648,0x9cb6afdd,0xaddcafd4,0xafc91648,0xa875af91,0x2b5e2fbc,0x2f1a244e,0x2e3fab05,
0xab05aff4,0x244eafa0,0x2fbc28d5,0xaf91abb7,0x30002c32,0x26a12fff,0xa5db2ddc,0x30002515,0xaaaa2c5d,0xac32af6e,0xae7caf6e,0xaf8025db,0xad27afed,0x2e3f2dfe,0x2f021fd9,0x2e1fac07,
0xaf5aae5e,0xac5daf30,0x2eb59fd9,0xb000a44e,0x2e7ca30e,0x2ddc2e1f,0x1cb62f1a,0x2fc9a30e,0x217e2f46,0xaf02acb0,0xaf02aed0,0xaf1a2993,0xaf30ae99,0x2fbc29f1,0x2ee99648,0x2dfeac87,
0xafa0a515,0xafafa993,0x2d00aaaa,0xafa02765,0x2934ad96,0x2fed26a1,0x28142fd4,0x2f30a9f1,0x2c872fed,0xb0009fd9,0xaf6eadfe,0xae992c07,0xafffabb7,0x2fe6a17e,0x2ed0a17e,0x2ddcad00,
0xac322c87,0xaf462a4e,0x2993adba,0xae7c2c87,0xa875afed,0x2f1aab05,0x2b5e2ffc,0x2e3facd8,0x2f302e1f,0xaee92bb7,0xafbcad00,0xadfe2d27,0xaf6e9cb6,0x2eb5ac32,0x2eb5a515,0x2dbaad72,
0xaaaa2f5a,0xaed02e99,0xacb02e99,0x2f80ad96,0x2b5eaf30,0x2fafa44e,0x2d00ae5e,0xaf1a9fd9,0xac072f02,0xab05ad27,0xad4d2e1f,0x28142e3f,0x2c5daed0,0xa9f12fff,0x2d96addc,0x2c5dafe6,
0x28752f80,0xa8d52fe6,0xa8d52fc9,0x2e3faf46,0xa44eafd4,0x2f91adba,0x2b05af6e,0xafbc26a1,0x96482ffc,0xae99a44e,0xac872ee9,0x29f12d4d,0x2515aff8,0x1cb62f02,0x2d72ae3f,0x2c32aff8,
0x2eb52b05,0x2a4e2cd8,0x16482fed,0x2c5daffc,0xad72ad27,0x2cb0aff4,0x2765aff4,0xafff2b5e,0x2bb72e7c,0xaff82aaa,0xab5e2f80,0x2bb72c32,0xa814af6e,0x2b052c87,0x2d4dae99,0x2c07b000,
0x2feda8d5,0x2f30a30e,0x29342f02,0x2814afa0,0xafd49cb6,0x1648aed0,0x1648afe6,0xafdd2d72,0x2ed029f1,0xaf462eb5,0xa9932fdd,0x2cb029f1,0xad00ad4d,0x2e1f244e,0x2d27aee9,0x2bb7affc,
0x2d4daf02,0x2fbcae1f,0x2cd82d27,0x9fd9ae3f,0xaf5a2cb0,0xac87a993,0xa6a1af46,0xaf5a2ed0,0x2fffa5db,0xacb03000,0xa7653000,0x2d7226a1,0xaf1aa814,0x2fafa934,0x2d00af30,0x2b5eafed,
0x1648afbc,0x2c87affc,0x2e992934,0xa9f1ac07,0xac322faf,0xaf8028d5,0xaaaaae1f,0xae7c2faf,0x2f1aad72,0xa30e2ed0,0xa30e2fe6,0x2e1f1cb6,0xaffc26a1,0x2fedadba,0x2cd8af6e,0x2b05afd4,
0xad27ac32,0xa30ead72,0x2faf9cb6,0xad27a515,0x1fd92f6e,0xafbc2e99,0xacd8ac87,0xad4d3000,0x2c5dafbc,0x2a4e2b05,0x16482f91,0x2eb5a44e,0xaf802d00,0x2ed0afa0,0x2cb0afa0,0x2aaaafaf,
0xafe626a1,0xaddc1648,0x2fffaa4e,0xaed026a1,0x2d002c07,0xad272ffc,0xae1fa934,0xabb72fbc,0x1fd9afa0,0x2e5ea30e,0x244e2f02,0x2f30a8d5,0xadba2f46,0x2c87afe6,0x2c87afc9,0x2a4eaf80,
0xafff2d96,0xae7c2c5d,0xafc92c5d,0x2d72a9f1,0xa17e2dfe,0xaff42fbc,0xa8752ee9,0x2ff8af30,0x2fedad00,0xad4d2f1a,0x2f91ab5e,0x2e5eafaf,0x25dbae7c,0x16482993,0x29f1af46,0x25dbac32,
0xae3f2fff,0xaff82fc9,0xaff82e7c,0x2f02ad72,0x2c0725db,0xadfe2f5a,0x9fd92d96,0x2fedafdd,0x2f6eaf91,0xa6a12c07,0x2fd4acd8,0x2dbaaf30,0xa765ab5e,0x2aaaa30e,0x2993af02,0x2515ab5e,
0xa5db2dfe,0xad962ee9,0xaf5a2fbc,0x2fddaf30,0x2f46ab5e,0xa7652bb7,0x25152bb7,0x2f80aff8,0x2d00afc9,0x28d59cb6,0x2ff8addc,0x2d00ae7c,0xacd89648,0x2dfeac5d,0x2934aeb5,0x244eaa4e,
0x2c07217e,0x9fd92875,0xadfe2ff4,0x2fedaff8,0x2fddaf46,0x29f1a515,0x29f12765,0x2eb5af80,0x2515ad96,0x2ddcac87,0x2fffaeb5,0x2c32ad96,0xaf022b05,0x2fa0aee9,0x28d5ae5e,0x230ea934,
0x2f91ad00,0x2cd8ab5e,0xac072f1a,0x2f30afaf,0x2d96afc9,0x2eb5addc,0x2c879cb6,0x2d96ae7c,0xa993a6a1,0x2fc9af5a,0x2fe6af5a,0x2aaaac87,0xaff82e5e,0x2ff4affc,0x2875adfe,0x217ea814,
0x2f6eafed,0x2fd4af91,0xa6a12d4d,0x2dbaae5e,0x2515ad00,0x2fffaff8,0x2ddca8d5,0x2c32ad00,0xae1f2993,0x2fafafe6,0x2fafafc9,0x28d5aaaa,0xaf912fdd,0x2ee9af5a,0x2814ad96,0x1fd9a5db,
0x2b5eae7c,0x2f02af46,0x230e2993,0x2b5eac32,0xab059648,0x2e5eaeb5,0x2ee9ac5d,0x2934aa4e,0xafdd2e5e,0x2d96adfe,0x2f5aaffc,0x25dba814,0xaddc2faf,0x2cb0ad27,0x2765ad27,0x1cb6a30e,
0xa765a5db,0x2993a9f1,0x2aaa9648,0x2515a5db,0xaf022cd8,0x28d5a934,0x2fa0adfe,0x230ea44e,0xaf912ff8,0x2814a875,0x2ee9aff4,0x1fd9a17e,0xaa4e2ddc,0x26a1a765,0x26a1acb0,0x16489cb6,
0x2d722d96,0x25152c5d,0x2c322c5d,0x1cb6a9f1,0x2d272d4d,0xad00a814,0x2bb72c07,0x2e1f2b05,0x2cd82d00,0xaffcaf1a,0x2b052b5e,0x2fed2faf,0x2c872cb0,0xadbaaf80,0x2a4e2aaa,0x2c872ed0,
0x2e3f2ddc,0x2ff82ed0,0x2ff82fe6,0xaf02afff,0x2ee92e99,0x2d4d2f6e,0x2ffc3000,0xa44eac87,0x2f6e2f30,0xa6a12814,0x2fd42fed,0x2dba2934,0x2fc92fa0,0xaf46ad00,0x2f802faf,0x2fe62fa0,
0xac87ad4d,0x9648ac07,0x29f12814,0xae99ab05,0xa993ab5e,0x2ed02bb7,0x2cb02bb7,0xaf46aff8,0xa30ea765,0x2f1a2fff,0x2e1f2d72,0xa30eacb0,0x244e1648,0x1fd92c5d,0x2f302eb5,0x2e5e2a4e,
0xaee9ae1f,0xaffcaf02,0xad4dae3f,0x244e2d27,0xafddaf80,0xa9f1ae7c,0xa9f1ac32,0xaeb5aaaa,0xafe6b000,0x2d7225db,0x9cb6a6a1,0xaed0b000,0xaf02af91,0x2fa02fbc,0x28d5244e,0x230eab05,
0x2b052d00,0xa44e2b5e,0xafbcaf1a,0x2f912faf,0x16482765,0xafd4ad72,0xafddafff,0x16482cb0,0xaaaaa6a1,0xac32af5a,0xae7caf5a,0xaf80ac87,0xae1facd8,0x2d001fd9,0xabb7ad4d,0xad27afbc,
0x2f6e2e5e,0x2fd42f30,0xa6a11fd9,0x2dba244e,0x2fe62ff4,0x1cb62d27,0xad72ab5e,0x2ed02ff4,0x2e1f2f46,0xafafacb0,0xafafaed0,0xa8d52993,0x29342c87,0xac07af6e,0xafbcb000,0xaffcae99,
0xa8d5acb0,0x2875aaaa,0x2e3f2f80,0xa8d5aed0,0x29341648,0x2fed2eb5,0x28142c5d,0x2f302a4e,0x2e992cd8,0x16482d4d,0xa9f19fd9,0x2c872fbc,0x2fff2faf,0xafe6ad27,0xaed0ad27,0xaddca30e,
0xafc9ae99,0xaf80af5a,0x2f462d96,0xafe6ae99,0xaf02afed,0x28d5ab05,0x2fa02ffc,0x230eacd8,0xa934ad27,0x2fbc2f02,0x2c072e3f,0x2ffc2e1f,0x2a4e1cb6,0xa6a12c32,0xa6a12515,0x96482d72,
0xaaaa29f1,0xaed025db,0xacb025db,0x2f801648,0xaf1aaf91,0x2875ae5e,0xae3fafed,0xab5e2d4d,0x2c07a875,0x2b052ff8,0x2d4da17e,0xa814aff4,0x2eb52fc9,0xaf6ead72,0x2dba2fff,0x2eb52e7c,
0x2f022f80,0x2b5e2fe6,0x2b5e2fc9,0x230eaf46,0xacd826a1,0xaf30ad96,0xaf91a9f1,0x2c072fd4,0xad96affc,0x2fdd244e,0xa5dbaee9,0xaf5aad4d,0x2e7c217e,0xad722bb7,0x2fff2d00,0x2fc9217e,
0x2c5da934,0x2f5aa44e,0x30002cd8,0xaeb5adfe,0x2d722ff8,0xacb02d00,0xa7652d00,0x2fff28d5,0xaf02a515,0x217eaf80,0xaf1aaf46,0xaf022765,0xa814af5a,0x2b052fdd,0x2d4da5db,0x2c07ad96,
0xae5eafa0,0xa934aff4,0x2b05abb7,0xaee928d5,0x2eb51cb6,0x2d962ed0,0x2d962fe6,0x2c87ad72,0x27652f6e,0xaf80ac5d,0xaf46a5db,0xa5152f6e,0xaff4ad4d,0x2ff8244e,0xa17eaee9,0xa875affc,
0xad4d2875,0xafbc217e,0xacd8aff8,0x1fd92ff4,0xaa4eafe6,0x2e99aaaa,0x2fd42993,0xaa4eafc9,0x2fff2c87,0xacb02d96,0xa7652d96,0x2d722eb5,0xab5e2c07,0x2875af30,0xae3faf91,0xaf1aacd8,
0x2d962fbc,0x25db2ffc,0xafdda934,0x2f5a2c07,0xafc9a875,0xaaaaafa0,0x2993ad27,0xafe6a875,0x28d5ad72,0x2d002ed0,0x2d002fe6,0x2ff81cb6,0x2d4d2fd4,0xae5ead96,0xafeda9f1,0xaf9126a1,
0x2e1fa765,0x2ff49cb6,0xa8752ddc,0x2e1facb0,0x1fd92f5a,0xafbc25db,0xacd8afdd,0xad4d2d96,0xaeb5aee9,0x2f5aa934,0x30002b05,0x2c5dae5e,0x2f80230e,0xaed02b5e,0xacb02b5e,0xaaaa2f02,
0xacb0afd4,0x9cb6b000,0x2ddc2f5a,0xa765afd4,0x2ff42c07,0x217e2ffc,0xaff8a934,0x28752fbc,0xadfe28d5,0xa44eaff4,0x2cd8abb7,0xa934afa0,0x1648af46,0x25db2fe6,0x25db2fc9,0x29f12f80,
0xafff9648,0xae7ca6a1,0xafc9a6a1,0x2d722a4e,0x2ff81fd9,0x230e2ee9,0x2faf2814,0x217eaf91,0xafeda30e,0x2d4dafa0,0xaf91a8d5,0xae5e2f02,0x2fdd2515,0xb0002aaa,0x2f6e2993,0x2fdda765,
0xa30e2fff,0xad272fc9,0xad272e7c,0x2fafad72,0x2814afdd,0x2ffcaa4e,0x2dfeadba,0xae5ea5db,0xaa4e2f91,0xac5dac07,0xaeb52cd8,0x96482f30,0x2c32af1a,0xa9932ff4,0x2f46abb7,0x2e7caf1a,
0x2fdd1fd9,0x2dba2814,0x2a4e2ee9,0x25dbaf91,0xaf46a8d5,0x2765afaf,0xa515afaf,0xaf802e1f,0x2e3f2c32,0xafa02ddc,0xa17e2fff,0x2e3f2515,0xacd8adba,0x2dfe26a1,0x2934afd4,0x244eaf6e,
0x2814aff8,0x2dfeafaf,0x2ffca30e,0xae5ea17e,0xac872f46,0xaf5a2515,0xaf5aa765,0xa6a12f80,0x2e7cadba,0x1cb62e99,0x2ddc2c5d,0x2fc9adba,0xafaf2b05,0x2f1aaee9,0xab5eae5e,0xad00a934,
0xaf91a30e,0xacd8a8d5,0x2c07afa0,0xaf302f02,0x2dba2c32,0xac5d2fff,0xae992ddc,0x2dba2515,0xa993aeb5,0x2fc9a9f1,0x2fe6a9f1,0x2aaaafdd,0xa17e2fed,0xa30eadfe,0xafaf9fd9,0xaff82c07,
0xaa4e2fed,0xaeb52f91,0xac5dad4d,0x96482e5e,0x2e7cae3f,0x2ddc217e,0x1cb62fa0,0x2fc9ae3f,0xaff82993,0x2bb7afe6,0x2bb7afc9,0xab5eaaaa,0x2f3025db,0xafbc2a4e,0xaee92dba,0xadfe2fdd,
0x2f1a2515,0x2bb72993,0xaff42aaa,0x2f1aa765,0xab05adba,0x2e5eafd4,0x2ee926a1,0x2934af6e,0xa5db2fed,0xadba9fd9,0xaa4eadfe,0xafdd2c07,0x2ddcaf02,0xacb02ff8,0xa7652ff8,0x9cb62e3f,
0x2c32afdd,0x2f46af6e,0xa9933000,0x2e7cafdd,0xafaf2cd8,0xab5ea934,0x2f1aadfe,0xad00a44e,0x2f30217e,0xaee92faf,0xafbc230e,0xadfe2ff8,0xa9f1addc,0x2c5d2765,0x2c5d2cb0,0x2d961cb6,
0xa993aa4e,0x2765ac87,0xa515ac87,0xaaaa2dba,0xafa02f30,0xabb7244e,0xaff42e5e,0x28d51fd9,0x28142bb7,0xaf912e1f,0x1fd92d27,0x2ee9ad00,0x2fd4aed0,0xaf5a2fff,0x3000addc,0x2fd4afe6,
0xafaf2f46,0xafa02e7c,0xafa02c32,0x2d00a993,0x244e2c5d,0xaf913000,0xab052f5a,0x2fbcaeb5,0x3000adfe,0xac872e5e,0x2e99a814,0x2f6eaffc,0x2515ae1f,0x1cb62875,0x2d72aff4,0x2c32ae1f,
0x26a12b05,0xa9f12cd8,0xad962fed,0x2fd4affc,0x2fffae1f,0x2515230e,0x2c32230e,0x2ddcaf1a,0x2875ae7c,0x2d27aaaa,0x2fa0af80,0x2875ac32,0xaee929f1,0x2f91ae99,0x9fd9ac87,0xa8149648,
0x2fedaf1a,0x2f30ae3f,0x29342875,0x2814ab5e,0x26a1addc,0x3000afc9,0x3000ae7c,0xa5db9cb6,0xaed02a4e,0x2f46afd4,0x2993ae99,0xacb02a4e,0xae3f2ffc,0x2d27ae5e,0xae1f2814,0xaf022dfe,
0x9fd9abb7,0x2c07ad27,0x2fedae1f,0xadfe2d00,0xaf6e2cb0,0x25dba993,0x2c5daf46,0xaf6e2ed0,0xaddc2fdd,0xa5159648,0xac329648,0xafff2fd4,0x28d52814,0xabb72934,0xaff42f30,0xafa02fed,
0xb0002ee9,0xae992dfe,0x2c87af30,0xaf6e2fbc,0xac322f02,0xaf802f1a,0xaaaaa17e,0xae7c2f02,0x2b5e1cb6,0xaff42fc9,0xaff42e7c,0xad272ddc,0x2ffcaeb5,0xafed3000,0xacd82f5a,0xab052c5d,
0xa17e2c32,0xad002d72,0xabb71cb6,0xa17e2515,0x2dfea9f1,0xac072c87,0xafed2e99,0x1fd91648,0x2fd4afbc,0xa9f12b05,0xad962f91,0x26a1a44e,0x2aaaae3f,0xa76528d5,0x251528d5,0x2993a875,
0x2fe6aeb5,0x2ddcadba,0xafff2f6e,0x2ed0aeb5,0x2e3fafbc,0x2e1fadfe,0xad272f30,0x2f02aee9,0x1fd9ab5e,0x2e5eae3f,0x244e2875,0x2f30af1a,0xad962993,0x2e99ae7c,0x2e99ac32,0x2f5aaf46,
0x299329f1,0xa76525db,0x251525db,0x2aaa1648,0x28d52934,0xaf02acd8,0x230e244e,0x2fa02dfe,0x28142875,0xaf91aff8,0x1fd9217e,0x2ee92ff4,0x26a12765,0xaa4eaddc,0x16481cb6,0x26a12cb0,
0x2f022f46,0x2b5e2e7c,0x2b5e2c32,0x230ea993,0x2e5e2eb5,0xab051648,0x29342a4e,0x2ee92c5d,0x2d962dfe,0xafddae5e,0x25db2814,0x2f5a2ffc,0x2cb02d27,0xaddcafaf,0x1cb6230e,0x27652d27,
0x2fd42f91,0x2f6e2fed,0x2dba2e5e,0xa6a1ad4d,0x2fff2ff8,0x25152d00,0x2c322d00,0x2ddc28d5,0x2faf2fe6,0xae1fa993,0x28d52aaa,0x2faf2fc9,0x2ee92f5a,0xaf91afdd,0x1fd925db,0x28142d96,
0x2cd82b5e,0x2f912d00,0x2f302faf,0xac07af1a,0x2eb52ddc,0x2d962fc9,0x2d962e7c,0x2c871cb6,0x2fc92f5a,0xa99326a1,0x2aaa2c87,0x2fe62f5a,0x2ff42ffc,0xaff8ae5e,0x217e2814,0x28752dfe,
0x9fd9a875,0x2c07a17e,0x2fed2ff8,0xadfeaff4,0x29f12515,0x2fdd2f46,0x2eb52f80,0x29f1a765,0x2ddc2c87,0x25152d96,0x2c322d96,0x2fff2eb5,0x2fa02ee9,0xaf02ab05,0x230e2934,0x28d52e5e,
0xad96aee9,0xa5dbadfe,0x2fdd2f30,0xaf5aafbc,0xa765abb7,0x2f462b5e,0x2f802ff8,0x2515abb7,0x28d51cb6,0x2d002fc9,0x2d002e7c,0x2ff82ddc,0x2dfe2c5d,0xacd81648,0x244e2a4e,0x29342eb5,
0xaff8afc9,0xae3fafff,0x2f022d72,0xaff8ae7c,0xadfeaf5a,0x2c07a5db,0x2fed2fdd,0x9fd9ad96,0xa6a1ac07,0x2f6e2f91,0x2dba2f30,0x2fd42cd8,0x2aaa230e,0xa7652b5e,0x25152b5e,0x29932f02,
0xae7cac5d,0xafffad96,0x2d7229f1,0xafc9ac5d,0xaff4afbc,0xa17eadfe,0x2ff82f30,0xa875aee9,0xad4daf1a,0x2fed2d00,0x2e5e2faf,0x2f912b5e,0x1648a993,0x25db2e7c,0x25db2c32,0x29f12f46,
0xaddc9648,0xafe6a6a1,0xaed0a6a1,0x2fff2a4e,0xad27affc,0x2d00ac07,0xabb7afbc,0xae1f2934,0x2e5e230e,0x1fd92fa0,0x2f3028d5,0x244eaf02,0x2c872fe6,0xadbaaf46,0x2a4e2f80,0x2c872fc9,
0xa30e2d72,0xad272c32,0xad272515,0x2faf1cb6,0xafbcae99,0x1fd9af6e,0xad4db000,0xacd82c87,0x2a4eab05,0x2c5d2fbc,0x2eb5244e,0x1648af91,0x2ed02fa0,0xaf80ad00,0x2aaa2faf,0x2cb02fa0,
0x2c872ffc,0x16482fbc,0xa9f12c07,0x2e99a934,0xaf80a8d5,0xac32afaf,0xae7cafaf,0xaaaa2e1f,0xa30eaed0,0x2f1a2d72,0x2e1f9cb6,0xa30eafe6,0x2fed2dba,0xaffca6a1,0x2b052fd4,0x2cd82f6e,
0x2fbc2e1f,0x2d4d2f02,0x9fd92e3f,0x2cd8ad27,0xac872993,0xaf5aacb0,0xaf5aaed0,0xa6a12f46,0xacb0b000,0x2fff25db,0x2d72a6a1,0xa765b000,0x2faf2934,0xaf1a2814,0x2b5e2fed,0x2d002f30,
0x2f30230e,0x2fed28d5,0x28142fa0,0x2934af02,0x16482ed0,0xafd41cb6,0xafddad72,0x16482fe6,0xaf46aeb5,0x2ed0a9f1,0x2cb0a9f1,0xa993afdd,0x2e1fa44e,0xad002d4d,0x2bb72ffc,0x2d272ee9,
0x2a4eacd8,0x2eb5ab05,0x2c5d2ffc,0x1648afed,0x2cb02ff4,0xad722d27,0xafffab5e,0x27652ff4,0xaff8aaaa,0x2bb7ae7c,0x2bb7ac32,0xab5eaf80,0x2b05ac87,0xa8142f6e,0x2c073000,0x2d4d2e99,
0xa8d5afe6,0x2875af80,0x2e3f2f46,0xa8d5afc9,0x2f912dba,0xa44e2fd4,0xafbca6a1,0x2b052f6e,0xae99244e,0x9648affc,0x29f1ad4d,0xac87aee9,0x1cb6af02,0x25152ff8,0x2c322ff8,0x2d722e3f,
0xaed0ae99,0xaaaaaf5a,0x2f802d96,0xacb0ae99,0x2faf244e,0x2b5e2f30,0xaf1a1fd9,0x2d002e5e,0xab052d27,0xac07af02,0x2814ae3f,0xad4dae1f,0xa9f1afff,0x2c5d2ed0,0x2c5d2fe6,0x2d962ddc,
0xaf46aa4e,0xac32ac87,0xae7cac87,0x29932dba,0x2f1a2b05,0xa8752fed,0x2e3f2cd8,0x2b5eaffc,0xaee9abb7,0x2f30ae1f,0xadfead27,0xafbc2d00,0x2eb52c32,0xaf6e1cb6,0x2dba2d72,0x2eb52515,
0xafaf2993,0xafa02515,0xafa0a765,0x2d002aaa,0x2feda6a1,0x29342d96,0x2f3029f1,0x2814afd4,0xb0001fd9,0x2c87afed,0xae99ac07,0xaf6e2dfe,0x2fe6217e,0xafff2bb7,0x2ddc2d00,0x2ed0217e,
0xac5d2f30,0xaf5a2e5e,0xb000244e,0x2eb51fd9,0x2ddcae1f,0x2e7c230e,0x2fc9230e,0x1cb6af1a,0xaf022cb0,0x217eaf46,0xaf1aa993,0xaf022ed0,0x2fbca9f1,0xaf302e99,0x2dfe2c87,0x2ee91648,
0x244e2fa0,0xab052ff4,0xaf912bb7,0x2fbca8d5,0x26a1afff,0x3000ac32,0x3000a515,0xa5dbaddc,0xac322f6e,0xaaaaac5d,0xaf80a5db,0xae7c2f6e,0x2e3fadfe,0xad272fed,0x2e1f2c07,0x2f029fd9,
0x2dfe2bb7,0x28142d27,0xae5e2e1f,0x2ffcad00,0xaa4eae7c,0x2e99af80,0x2fd4aaaa,0xaa4eac32,0x9cb62fdd,0xae7c9648,0xafc99648,0xaddc2fd4,0x2b5eafbc,0xa8752f91,0x2e3f2b05,0x2f1aa44e,
0x3000a814,0x2e999fd9,0xac872f91,0x2f6eaee9,0xaed0a875,0x2993afa0,0x2f46ad27,0xacb0a875,0x2b5e2ddc,0xaff42c32,0xaff42515,0xad272fff,0x1fd9afd4,0x244e2d96,0x2e5e29f1,0x2f30a6a1,
0x2e1faed0,0x2ff4addc,0xa8752fff,0x2e1fafe6,0xaffc29f1,0xa814ac87,0x2e5eae99,0xadfe9648,0x2eb52814,0xaf5a2f30,0xb0002934,0xac5d2fed,0xa993ae3f,0x2c3228d5,0x2e7c28d5,0x2f46a875,
0x2515afd4,0x2d72b000,0x1cb62f5a,0x2c32afd4,0xae3f2ee9,0xae1f1fd9,0x2d27af91,0xaf022814,0x2ffca8d5,0xacd82ff4,0xafed2bb7,0xab052fa0,0xad96aaaa,0x2e99a515,0x2e992765,0x2f5aa993,
0x1cb6adba,0x2cb0aeb5,0x2765aeb5,0xaddc2f6e,0xaff82d4d,0xa30ea814,0xafaf2c07,0xa17e2b05,0xa44e2e3f,0xadfe2b5e,0xa9342f1a,0x2cd8a875,0x2fddacb0,0xb0002f80,0x2f6eaaaa,0x2fddaed0,
0xad009cb6,0xa17ea765,0xa17eacb0,0xabb72ddc,0xaee92fdd,0xad4d2a4e,0xaffc2dba,0x244e25db,0x29f12934,0xafd42ee9,0xa6a12e5e,0x2d96ab05,0x2fc9af1a,0xaf462ff4,0x2f80abb7,0x2fe6af1a,
0xafdd2d4d,0xadba2c07,0xaa4ea814,0xa5db2b05,0xaaaa2f1a,0xafc92f02,0xafe62f02,0x2993a17e,0x2e3fa765,0xafa02fff,0xa17e2d72,0x2e3facb0,0x2e5eb000,0xad4d2eb5,0x2f91ac5d,0x2fedaf5a,
0xaee92ff8,0xaffc2faf,0xad4d230e,0x244e217e,0x25db2aaa,0xaf6e2fe6,0xaf6e2fc9,0x2c5da993,0x2fe6adba,0xad722e99,0x1cb62c5d,0x2ed0adba,0x2bb7af30,0xa8d52c07,0x2fa0acd8,0x2ff4af91,
0xa9342e3f,0xae5e2f1a,0xaee92b5e,0x2b05a875,0x2dbaa765,0xac5d2d72,0xae992fff,0x2dbaacb0,0x2f80afd4,0xa7652a4e,0x25152a4e,0x2f46ae99,0x217eacd8,0x230e1fd9,0x2fafad4d,0x2ff8afbc,
0x29f1244e,0xa6a12934,0xafd42dfe,0x2d96acd8,0x2fe6ae3f,0x1cb6217e,0xad722fa0,0x2ed0ae3f,0x2d27af80,0x2875a515,0x28752765,0x2fa0af46,0xa934a5db,0x2c07aa4e,0x2fbcadba,0x2ffcafdd,
0x2f1aacb0,0x2bb7aaaa,0xaff42f80,0x2f1aaed0,0x2f30b000,0x2cd8ac5d,0xac072eb5,0x2f91af5a,0x25dbacd8,0x2dbaad4d,0x2a4e1fd9,0x2fddafbc,0xad722875,0x2e7cae1f,0x2fc9ae1f,0x2fffaff4,
0x2fc9afdd,0x2f80af6e,0xaf463000,0x2fe6afdd,0x2bb7ae5e,0x2fa0af91,0xa8d52d4d,0x2ff4afed,0xa934a17e,0x2fbcafaf,0x2c07a30e,0x2ffcaff8,0xaf5a2d72,0x2fd4afc9,0x2fd4ae7c,0x3000afff,
0x9d4d9e16,0xada6ae7d,0x9b769c84,0xabf0accf,0x985299e4,0xa897aa43,0x90b6957f,0xa102a5d8,0x13db0a48,0x242c1aad,0x191b1712,0x296d2783,0x1c201aad,0x2c632b1a,0x1db21ce9,0x2e112d3a,
0xa3f4a491,0xae51af42,0xa199a2c6,0xac70ad60,0x9e7ba06b,0xa922ab00,0x97129c20,0xa199a688,0x19e410b6,0x24aa1b76,0x1fa81d4d,0x2a112833,0x222f2102,0x2ce82bf0,0x2445235d,0x2ec92dd8,
0xa6a1a79c,0xaefcb004,0xa4aaa5a5,0xace8adf2,0xa166a35d,0xa9acabbe,0x99e49edf,0xa22fa738,0x1ce913db,0x25281c20,0x2262206b,0x2ab528a4,0x2528242c,0x2d6d2c63,0x271f2623,0x2f822e77,
0xa8a4a954,0xafa8b067,0xa688a7e8,0xad60ae84,0xa38fa528,0xaa37ac3d,0x9c20a0d0,0xa2c6a7e8,0x1edf157f,0x25a51c84,0x2478222f,0x2b592915,0x273825d8,0x2df22ccf,0x28fc284c,0x301d2f16,
0xa9f8aadb,0xb02ab0ca,0xa833a915,0xadd8af16,0xa4dca6a1,0xaac1ac9c,0x9d4da22f,0xa35da84c,0x206b1712,0x26231ce9,0x25bf23f4,0x2bfd2987,0x28a42783,0x2e772d3a,0x2a692987,0x307a2fb5,
0xab4cac31,0xb081b12e,0xa922aa37,0xae51afa8,0xa5f1a80d,0xab4cacfb,0x9e7ba38f,0xa3f4a8a4,0x21661852,0x26a11d4d,0x270524dc,0x2c5029f8,0x29ac2897,0x2efc2da6,0x2bd72ac1,0x30d7302a,
0xac50acf5,0xb0d7b192,0xaa11ab59,0xaec9b01d,0xa705a8ca,0xabd7ad5a,0x9fa8a478,0xa445a8fc,0x2262191b,0x271f1db2,0x282625bf,0x2ca22a69,0x2ab5296d,0x2f822e11,0x2ca22bfd,0x3135307a,
0xacfbadb9,0xb12eb1f7,0xab00ac3d,0xaf42b067,0xa80da987,0xac31adb9,0xa06ba528,0xa491a954,0x235d19e4,0x279c1e16,0x28ca26a1,0x2cf52adb,0x2bbe2a43,0x30042e7d,0x2d5a2c9c,0x319230ca,
0xb185b25c,0xb426b4cc,0xafbbb0b1,0xb1c6b306,0xac76ae18,0xaea3b08a,0xa4dca9ac,0xa738ac37,0x280d1e7b,0x2a0520d0,0x2d472b4c,0x2fdb2d6d,0x30472ee9,0x32663128,0x31f0311b,0x347933a8,
0xb1ddb2c1,0xb453b501,0xb01ab0fb,0xb204b352,0xacbcae77,0xaee9b0ba,0xa528aa05,0xa783ac63,0x284c1edf,0x2a432102,0x2d992bbe,0x30172da6,0x308a2f55,0x32aa315f,0x324f316b,0x34aa33fc,
0xb235b327,0xb481b537,0xb057b145,0xb242b39e,0xad01aed6,0xaf2fb0eb,0xa573aa5d,0xa7cfac90,0x288b1f44,0x2a822134,0x2deb2c18,0x30412ddf,0x30ce2fc2,0x32ef3196,0x32ae31bc,0x34db3428,
0xb28db38e,0xb4afb56d,0xb094b18f,0xb280b3eb,0xad47af36,0xaf75b11b,0xa5bfaab5,0xa80dacbc,0x28ca1fa8,0x2ac12166,0x2e3e2c50,0x306a2e18,0x31113017,0x333531cd,0x330d320e,0x350d3452,
0xb2e5b3f5,0xb4ddb5a3,0xb0d1b1da,0xb2beb41c,0xad8caf95,0xafbbb14b,0xa60aab0d,0xa833ace8,0x29092006,0x2b002199,0x2e902c89,0x30942e51,0x3155304d,0x337a3204,0x336d325f,0x3540347c,
0xb33eb42e,0xb50cb5da,0xb10eb224,0xb2fcb443,0xadd2aff5,0xb001b17c,0xa655ab65,0xa859ad14,0x29482039,0x2b4021cb,0x2ee32cc2,0x30be2e8a,0x31993084,0x33c0323b,0x33cd32b1,0x357234a6,
0xb398b463,0xb53ab612,0xb14bb26f,0xb33bb469,0xae18b02a,0xb024b1ac,0xa6a1abbe,0xa87ead40,0x2987206b,0x2b7f21fd,0x2f362cfb,0x30e72ec3,0x31dd30ba,0x34033273,0x34173303,0x35a534d1,
0xb3f2b497,0xb569b64a,0xb189b2bb,0xb37ab490,0xae5eb05a,0xb047b1dd,0xa6ecac0b,0xa8a4ad6d,0x29c6209d,0x2bbe222f,0x2f882d34,0x31112efc,0x322130f1,0x342632aa,0x34483356,0x35d934fc,
0xb599b682,0xb722b82e,0xb3b9b4b7,0xb4ddb5f9,0xb06ab20e,0xb185b398,0xa8caad99,0xa9f8aefc,0x2bfd2262,0x2cfb23f4,0x313b2f36,0x328d3081,0x344932e2,0x35693453,0x360d3527,0x37bd368b,
0xb5c9b6bb,0xb755b84d,0xb3f8b4df,0xb4feb622,0xb08db23e,0xb1a9b3ca,0xa8f0adc5,0xaa1eaf29,0x2c1e2294,0x2d1b2413,0x31652f6f,0x32b7309d,0x346d331a,0x358e3470,0x36413553,0x37f536ba,
0xb5f9b6f5,0xb789b86d,0xb41cb506,0xb51fb64c,0xb0b1b26f,0xb1cdb3fc,0xa915adf2,0xaa43af55,0x2c3d22c6,0x2d3a242c,0x318f2fa8,0x32e230ba,0x34903352,0x35b3348d,0x3676357e,0x381736e8,
0xb629b72f,0xb7bdb88d,0xb43cb52e,0xb540b676,0xb0d4b2a1,0xb1f0b417,0xa93bae1e,0xaa69af82,0x2c5d22f9,0x2d5a2445,0x31b92fe2,0x330d30d7,0x34b4338b,0x35d934aa,0x36ab35ab,0x38343717,
0xb65ab76a,0xb7f1b8ad,0xb45cb556,0xb561b6a0,0xb0f7b2d2,0xb214b430,0xa961ae4b,0xaa8fafaf,0x2c7d232b,0x2d79245f,0x31e3300e,0x333830f4,0x34d833c3,0x35fe34c7,0x36e035d7,0x38513746,
0xb68bb7a5,0xb813b8ce,0xb47cb57e,0xb582b6ca,0xb11bb303,0xb238b449,0xa987ae77,0xaab5afdb,0x2c9c235d,0x2d992478,0x320e302a,0x33633111,0x34fc33fc,0x362434e4,0x37173604,0x386f3775,
0xb6bdb7e2,0xb82eb8f0,0xb49cb5a7,0xb5a3b6f5,0xb13eb335,0xb25cb463,0xa9acaea3,0xaadbb004,0x2cbc238f,0x2db92491,0x32383047,0x338e312e,0x3520341a,0x364a3501,0x374d3631,0x388d37a5,
0xb6efb80f,0xb849b911,0xb4bdb5d0,0xb5c5b720,0xb162b366,0xb280b47c,0xa9d2aed0,0xab00b01a,0x2cdb23c2,0x2dd824aa,0x32623064,0x33b9314b,0x35453437,0x3670351f,0x3785365e,0x38ab37d6,
0xb865b934,0xb94dba5c,0xb5e7b74c,0xb6fcb85a,0xb2a4b495,0xb3c6b564,0xab26b031,0xac2bb0e4,0x2df824c3,0x2ef6258c,0x33e43168,0x34a13252,0x3697353c,0x37d4362d,0x38ca3803,0x39d038d0,
0xb880b957,0xb96bba84,0xb609b777,0xb720b872,0xb2c8b4af,0xb3ebb57e,0xab4cb047,0xac3db0fb,0x2e1824dc,0x2f1625a5,0x34083185,0x34b7326f,0x36bd355a,0x37fd364c,0x38e9381c,0x39f338eb,
0xb89cb97a,0xb98abaad,0xb62bb7a4,0xb744b88a,0xb2ecb4c9,0xb408b599,0xab72b05d,0xac50b111,0x2e3724f5,0x2f3625bf,0x341e31a2,0x34ce328d,0x36e43577,0x3813366b,0x39093835,0x3a173906,
0xb8b9b99e,0xb9aabad7,0xb64db7d0,0xb768b8a2,0xb310b4e2,0xb41ab5b3,0xab98b074,0xac63b128,0x2e57250f,0x2f5525d8,0x343331c0,0x34e432aa,0x370b3595,0x3828368a,0x3929384e,0x3a3b3922,
0xb8d6b9c3,0xb9cabb02,0xb670b7fd,0xb78cb8ba,0xb335b4fc,0xb42db5ce,0xabbeb08a,0xac76b13e,0x2e772528,0x2f7525f1,0x344931dd,0x34fa32c8,0x373335b3,0x383d36a9,0x39493868,0x3a60393e,
0xb8f3b9e8,0xb9ebbb2d,0xb693b815,0xb7b1b8d2,0xb359b516,0xb43fb5e9,0xabe3b0a1,0xac89b155,0x2e972541,0x2f95260a,0x345f31fa,0x351132e5,0x375b35d2,0x385236c8,0x396a3881,0x3a86395a,
0xb910ba0e,0xba0cbb59,0xb6b6b82c,0xb7d6b8eb,0xb37db530,0xb452b604,0xac05b0b7,0xac9cb16b,0x2eb6255a,0x2fb52623,0x34753217,0x35273303,0x378335f0,0x386836e8,0x398c389b,0x3aac3977,
0xb92eba35,0xba2dbb87,0xb6d9b843,0xb7fbb904,0xb3a2b54a,0xb464b61e,0xac18b0ce,0xacafb182,0x2ed62573,0x2fd5263c,0x348b3235,0x353e3321,0x37ab360e,0x387d3708,0x39ae38b6,0x3ad33994,
0x9ce99db2,0xad3aae11,0x9aad9c20,0xab1aac63,0x9712991b,0xa783a96d,0x8a4893db,0x9aada42c,0x157f10b6,0x25d82102,0x19e41852,0x2a432897,0x1c841b76,0x2ccf2bf0,0x1e161d4d,0x2e7d2da6,
0xa35da445,0xadd8aec9,0xa102a22f,0xabf0ace8,0x9d4d9fa8,0xa833aa11,0x90b699e4,0x9b76a4aa,0x1c201712,0x26882199,0x206b1e7b,0x2b002922,0x22c62199,0x2d602c70,0x249123f4,0x2f422e51,
0xa623a71f,0xae77af82,0xa42ca528,0xac63ad6d,0xa06ba262,0xa8a4aab5,0x93db9ce9,0x9c20a528,0x1edf19e4,0x2738222f,0x235d2166,0x2bbe29ac,0x25a524aa,0x2df22ce8,0x279c26a1,0x30042efc,
0xa84ca8fc,0xaf16b01d,0xa5d8a738,0xaccfadf2,0xa22fa478,0xa915ab59,0x957f9edf,0x9c84a5a5,0x20d01c20,0x27e822c6,0x2528238f,0x2c3d2a37,0x27e82688,0x2e842d60,0x295428a4,0x30672fa8,
0xa987aa69,0xafb5b07a,0xa783a8a4,0xad3aae77,0xa3f4a5bf,0xa987abfd,0x9712a06b,0x9ce9a623,0x222f1d4d,0x284c235d,0x26a124dc,0x2c9c2ac1,0x29152833,0x2f162dd8,0x2adb29f8,0x30ca302a,
0xaac1abd7,0xb02ab0d7,0xa897a9ac,0xada6aefc,0xa4dca705,0xa9f8ac50,0x9852a166,0x9d4da6a1,0x238f1e7b,0x28a423f4,0x280d25f1,0x2cfb2b4c,0x2a372922,0x2fa82e51,0x2c312b4c,0x312e3081,
0xabfdaca2,0xb07ab135,0xa96daab5,0xae11af82,0xa5bfa826,0xaa69aca2,0x991ba262,0x9db2a71f,0x24781fa8,0x28fc2445,0x28ca2705,0x2d5a2bd7,0x2b592a11,0x301d2ec9,0x2cf52c50,0x319230d7,
0xac9cad5a,0xb0cab192,0xaa43abbe,0xae7db004,0xa6a1a8ca,0xaadbacf5,0x99e4a35d,0x9e16a79c,0x2528206b,0x29542491,0x2987280d,0x2db92c31,0x2c3d2b00,0x30672f42,0x2db92cfb,0x31f7312e,
0xb11bb1f0,0xb3a8b479,0xaee9b047,0xb128b266,0xab4cad47,0xad6dafdb,0x9e7ba80d,0xa0d0aa05,0x29ac24dc,0x2c372738,0x2e182c76,0x308a2ea3,0x30b12fbb,0x330631c6,0x325c3185,0x34cc3426,
0xb16bb24f,0xb3fcb4aa,0xaf55b08a,0xb15fb2aa,0xabbead99,0xada6b017,0x9edfa84c,0xa102aa43,0x2a052528,0x2c632783,0x2e772cbc,0x30ba2ee9,0x30fb301a,0x33523204,0x32c131dd,0x35013453,
0xb1bcb2ae,0xb428b4db,0xafc2b0ce,0xb196b2ef,0xac18adeb,0xaddfb041,0x9f44a88b,0xa134aa82,0x2a5d2573,0x2c9027cf,0x2ed62d01,0x30eb2f2f,0x31453057,0x339e3242,0x33273235,0x35373481,
0xb20eb30d,0xb452b50d,0xb017b111,0xb1cdb335,0xac50ae3e,0xae18b06a,0x9fa8a8ca,0xa166aac1,0x2ab525bf,0x2cbc280d,0x2f362d47,0x311b2f75,0x318f3094,0x33eb3280,0x338e328d,0x356d34af,
0xb25fb36d,0xb47cb540,0xb04db155,0xb204b37a,0xac89ae90,0xae51b094,0xa006a909,0xa199ab00,0x2b0d260a,0x2ce82833,0x2f952d8c,0x314b2fbb,0x31da30d1,0x341c32be,0x33f532e5,0x35a334dd,
0xb2b1b3cd,0xb4a6b572,0xb084b199,0xb23bb3c0,0xacc2aee3,0xae8ab0be,0xa039a948,0xa1cbab40,0x2b652655,0x2d142859,0x2ff52dd2,0x317c3001,0x3224310e,0x344332fc,0x342e333e,0x35da350c,
0xb303b417,0xb4d1b5a5,0xb0bab1dd,0xb273b403,0xacfbaf36,0xaec3b0e7,0xa06ba987,0xa1fdab7f,0x2bbe26a1,0x2d40287e,0x302a2e18,0x31ac3024,0x326f314b,0x3469333b,0x34633398,0x3612353a,
0xb356b448,0xb4fcb5d9,0xb0f1b221,0xb2aab426,0xad34af88,0xaefcb111,0xa09da9c6,0xa22fabbe,0x2c0b26ec,0x2d6d28a4,0x305a2e5e,0x31dd3047,0x32bb3189,0x3490337a,0x349733f2,0x364a3569,
0xb527b60d,0xb68bb7bd,0xb2e2b449,0xb453b569,0xaf36b13b,0xb081b28d,0xa262abfd,0xa3f4acfb,0x2d9928ca,0x2efc29f8,0x320e306a,0x33983185,0x34b733b9,0x35f934dd,0x36823599,0x382e3722,
0xb553b641,0xb6bab7f5,0xb31ab46d,0xb470b58e,0xaf6fb165,0xb09db2b7,0xa294ac1e,0xa413ad1b,0x2dc528f0,0x2f292a1e,0x323e308d,0x33ca31a9,0x34df33f8,0x362234fe,0x36bb35c9,0x384d3755,
0xb57eb676,0xb6e8b817,0xb352b490,0xb48db5b3,0xafa8b18f,0xb0bab2e2,0xa2c6ac3d,0xa42cad3a,0x2df22915,0x2f552a43,0x326f30b1,0x33fc31cd,0x3506341c,0x364c351f,0x36f535f9,0x386d3789,
0xb5abb6ab,0xb717b834,0xb38bb4b4,0xb4aab5d9,0xafe2b1b9,0xb0d7b30d,0xa2f9ac5d,0xa445ad5a,0x2e1e293b,0x2f822a69,0x32a130d4,0x341731f0,0x352e343c,0x36763540,0x372f3629,0x388d37bd,
0xb5d7b6e0,0xb746b851,0xb3c3b4d8,0xb4c7b5fe,0xb00eb1e3,0xb0f4b338,0xa32bac7d,0xa45fad79,0x2e4b2961,0x2faf2a8f,0x32d230f7,0x34303214,0x3556345c,0x36a03561,0x376a365a,0x38ad37f1,
0xb604b717,0xb775b86f,0xb3fcb4fc,0xb4e4b624,0xb02ab20e,0xb111b363,0xa35dac9c,0xa478ad99,0x2e772987,0x2fdb2ab5,0x3303311b,0x34493238,0x357e347c,0x36ca3582,0x37a5368b,0x38ce3813,
0xb631b74d,0xb7a5b88d,0xb41ab520,0xb501b64a,0xb047b238,0xb12eb38e,0xa38facbc,0xa491adb9,0x2ea329ac,0x30042adb,0x3335313e,0x3463325c,0x35a7349c,0x36f535a3,0x37e236bd,0x38f0382e,
0xb65eb785,0xb7d6b8ab,0xb437b545,0xb51fb670,0xb064b262,0xb14bb3b9,0xa3c2acdb,0xa4aaadd8,0x2ed029d2,0x301a2b00,0x33663162,0x347c3280,0x35d034bd,0x372035c5,0x380f36ef,0x39113849,
0xb803b8ca,0xb8d0b9d0,0xb53cb697,0xb62db7d4,0xb168b3e4,0xb252b4a1,0xa4c3adf8,0xa58caef6,0x30312b26,0x30e42c2b,0x349532a4,0x356433c6,0x374c35e7,0x385a36fc,0x39343865,0x3a5c394d,
0xb81cb8e9,0xb8ebb9f3,0xb55ab6bd,0xb64cb7fd,0xb185b408,0xb26fb4b7,0xa4dcae18,0xa5a5af16,0x30472b4c,0x30fb2c3d,0x34af32c8,0x357e33eb,0x37773609,0x38723720,0x39573880,0x3a84396b,
0xb835b909,0xb906ba17,0xb577b6e4,0xb66bb813,0xb1a2b41e,0xb28db4ce,0xa4f5ae37,0xa5bfaf36,0x305d2b72,0x31112c50,0x34c932ec,0x35993408,0x37a4362b,0x388a3744,0x397a389c,0x3aad398a,
0xb84eb929,0xb922ba3b,0xb595b70b,0xb68ab828,0xb1c0b433,0xb2aab4e4,0xa50fae57,0xa5d8af55,0x30742b98,0x31282c63,0x34e23310,0x35b3341a,0x37d0364d,0x38a23768,0x399e38b9,0x3ad739aa,
0xb868b949,0xb93eba60,0xb5b3b733,0xb6a9b83d,0xb1ddb449,0xb2c8b4fa,0xa528ae77,0xa5f1af75,0x308a2bbe,0x313e2c76,0x34fc3335,0x35ce342d,0x37fd3670,0x38ba378c,0x39c338d6,0x3b0239ca,
0xb881b96a,0xb95aba86,0xb5d2b75b,0xb6c8b852,0xb1fab45f,0xb2e5b511,0xa541ae97,0xa60aaf95,0x30a12be3,0x31552c89,0x35163359,0x35e9343f,0x38153693,0x38d237b1,0x39e838f3,0x3b2d39eb,
0xb89bb98c,0xb977baac,0xb5f0b783,0xb6e8b868,0xb217b475,0xb303b527,0xa55aaeb6,0xa623afb5,0x30b72c05,0x316b2c9c,0x3530337d,0x36043452,0x382c36b6,0x38eb37d6,0x3a0e3910,0x3b593a0c,
0xb8b6b9ae,0xb994bad3,0xb60eb7ab,0xb708b87d,0xb235b48b,0xb321b53e,0xa573aed6,0xa63cafd5,0x30ce2c18,0x31822caf,0x354a33a2,0x361e3464,0x384336d9,0x390437fb,0x3a35392e,0x3b873a2d,
0x214d2216,0x319b326c,0x1f762084,0x2fe830c8,0x1c521de4,0x2c962e40,0x14b6197f,0x250229d7,0x97db8e48,0xa82c9ead,0x9d1b9b12,0xad6bab82,0xa0209ead,0xb05eaf14,0xa1b2a0e9,0xb204b131,
0x27f32890,0x3241332b,0x259826c6,0x306a3156,0x227b246b,0x2d202efb,0x1b122020,0x25982a87,0x9de494b6,0xa8aa9f76,0xa3a8a14d,0xae0eac32,0xa62fa502,0xb0e1afe8,0xa845a75d,0xb2b6b1cc,
0x2aa02b9b,0x32e733e8,0x28aa29a5,0x30e131e5,0x2566275d,0x2daa2fb6,0x1de422df,0x262f2b36,0xa0e997db,0xa927a020,0xa661a46b,0xaeb0aca2,0xa927a82c,0xb163b05e,0xab1daa22,0xb368b266,
0x2ca22d52,0x338d3452,0x2a872be6,0x31563273,0x278f2927,0x2e333039,0x202024cf,0x26c62be6,0xa2df997f,0xa9a5a084,0xa877a62f,0xaf53ad13,0xab36a9d7,0xb1e5b0c8,0xacfaac4b,0xb40cb300,
0x2df52ed6,0x341834b0,0x2c322d13,0x31cc3300,0x28dc2aa0,0x2ebd3096,0x214d262f,0x275d2c4b,0xa46b9b12,0xaa22a0e9,0xa9bea7f3,0xaff5ad84,0xaca2ab82,0xb266b131,0xae65ad84,0xb464b399,
0x2f46302c,0x346a350c,0x2d202e33,0x3241338d,0x29f02c0c,0x2f4630f3,0x227b278f,0x27f32ca2,0xa5669c52,0xaaa0a14d,0xab04a8dc,0xb04badf5,0xadaaac96,0xb2e7b19b,0xafcfaebd,0xb4bcb418,
0x304b30ed,0x34bc3568,0x2e0e2f53,0x32b6340c,0x2b042cc8,0x2fcf3150,0x23a82877,0x28452cfa,0xa6619d1b,0xab1da1b2,0xac25a9be,0xb09cae65,0xaeb0ad6b,0xb368b204,0xb09caff5,0xb512b464,
0x30f331ad,0x350c35c4,0x2efb3039,0x332b3452,0x2c0c2d84,0x302c31ad,0x246b2927,0x28902d52,0xa75d9de4,0xab9ba216,0xacc8aaa0,0xb0edaed6,0xafb6ae40,0xb3e8b26c,0xb150b096,0xb568b4b0,
0x355d361e,0x37c63867,0x339f3497,0x359836b4,0x3071320a,0x32913473,0x28dc2daa,0x2b363032,0xac0ca27b,0xae01a4cf,0xb13eaf46,0xb3bdb163,0xb434b2d5,0xb627b506,0xb5beb4fa,0xb826b73e,
0x35ac3678,0x3808388f,0x340934dd,0x35cf36f5,0x30b53266,0x32d534a0,0x29272e01,0x2b82305e,0xac4ba2df,0xae40a502,0xb18eafb6,0xb406b19b,0xb473b33d,0xb663b539,0xb612b545,0xb84cb784,
0x35fb36d0,0x382c38b7,0x34433521,0x36073736,0x30f932c2,0x331834ce,0x29722e59,0x2bcd308a,0xac89a344,0xae7ea534,0xb1dfb013,0xb42eb1d2,0xb4b3b3a5,0xb6a0b56b,0xb666b58f,0xb872b7c9,
0x36493728,0x385038de,0x347c3565,0x363e3776,0x313e331e,0x335c34fa,0x29be2eb0,0x2c0c30b5,0xacc8a3a8,0xaebda566,0xb22fb04b,0xb455b20a,0xb4f1b406,0xb6dcb59d,0xb6b9b5d8,0xb898b807,
0x3697377e,0x38743904,0x34b635a9,0x367537b6,0x3182337a,0x339f3527,0x2a092f08,0x2c3230e1,0xad07a406,0xaefba598,0xb27fb083,0xb47cb241,0xb530b43a,0xb717b5cf,0xb70cb621,0xb8bdb828,
0x36e437d4,0x3897392a,0x34ee35ed,0x36ab37f5,0x31c633d6,0x33e23554,0x2a542f5f,0x2c57310c,0xad45a439,0xaf3aa5cb,0xb2cfb0bb,0xb4a4b279,0xb56eb46d,0xb752b601,0xb75db669,0xb8e1b84a,
0x37303814,0x38b9394e,0x3527362f,0x36e1381a,0x320a3418,0x34123580,0x2aa02fb6,0x2c7d3137,0xad84a46b,0xaf78a5fd,0xb31eb0f3,0xb4cbb2b0,0xb5acb4a0,0xb78cb632,0xb7adb6b1,0xb905b86b,
0x377c383e,0x38db3972,0x355f3672,0x37173838,0x324e3446,0x343435ac,0x2aeb3007,0x2ca23163,0xadc3a49d,0xafb6a62f,0xb36eb12b,0xb4f1b2e7,0xb5eab4d4,0xb7c6b663,0xb7fdb6f8,0xb928b88b,
0x38fd3996,0x39f33a91,0x374c3857,0x3874393e,0x345535d8,0x355d3730,0x2cc8318e,0x2df532e7,0xaff5a661,0xb0f3a7f3,0xb518b31e,0xb649b46a,0xb800b694,0xb8dbb808,0xb94bb8ab,0xba45b99b,
0x391e39b8,0x3a0f3aad,0x37813875,0x388c3959,0x34763604,0x357d375a,0x2cee31b9,0x2e1a3312,0xb01aa694,0xb112a813,0xb53fb356,0xb66fb485,0xb81cb6c5,0xb8f5b81f,0xb96db8cb,0xba61b9b7,
0x393e39da,0x3a2b3ac7,0x37b63893,0x38a53974,0x3497362f,0x359d3784,0x2d1331e5,0x2e40333d,0xb039a6c6,0xb131a82c,0xb565b38d,0xb694b4a0,0xb838b6f5,0xb90fb836,0xb98eb8ea,0xba7cb9d2,
0x395e39fb,0x3a453ae0,0x37ea38b0,0x38bd398e,0x34b9365b,0x35be37ad,0x2d393210,0x2e653368,0xb058a6f8,0xb150a845,0xb58cb3c3,0xb6b9b4bc,0xb854b725,0xb928b84c,0xb9aeb909,0xba97b9ed,
0x397d3a1b,0x3a5f3af9,0x380f38cd,0x38d539a8,0x34da3686,0x35de37d7,0x2d5e323b,0x2e8b3393,0xb077a72a,0xb16fa85e,0xb5b2b3fa,0xb6deb4d7,0xb870b755,0xb941b863,0xb9ceb927,0xbab0ba07,
0x399b3a3a,0x3a793b10,0x382838ea,0x38ed39c1,0x34fa36b1,0x35fe3800,0x2d843266,0x2eb033bd,0xb096a75d,0xb18ea877,0xb5d8b418,0xb703b4f1,0xb88bb784,0xb95ab879,0xb9edb945,0xbac9ba21,
0x39b93a58,0x3a913b26,0x38423906,0x390439da,0x351b36dc,0x361e3814,0x2daa3291,0x2ed633e8,0xb0b5a78f,0xb1ada890,0xb5feb434,0xb728b50c,0xb8a6b7b3,0xb972b88f,0xba0bb962,0xbae0ba3a,
0x39d73a75,0x3aa93b3c,0x385b3922,0x391b39f2,0x353c3706,0x363e3828,0x2dcf32bc,0x2efb3409,0xb0d4a7c1,0xb1cca8aa,0xb624b44f,0xb74cb527,0xb8c1b7e2,0xb98ab8a5,0xba29b97f,0xbaf7ba52,
0x3ac03b50,0x3b5e3bcb,0x39323a0a,0x39de3ab8,0x365e383c,0x375738d7,0x2f21341f,0x302634c8,0xb1eba8c3,0xb2e1a98c,0xb770b542,0xb846b615,0xb9a2b8bb,0xba51b960,0xbb0dba6a,0xbb9cbb11,
0x3ad73b63,0x3b6e3bd6,0x39493a22,0x39f23acb,0x367d3850,0x377638ea,0x2f463434,0x303934dd,0xb20aa8dc,0xb300a9a5,0xb795b55d,0xb857b62f,0xb9b9b8d0,0xba65b974,0xbb22ba81,0xbba9bb24,
0x3aec3b75,0x3b7d3bdf,0x395f3a39,0x3a063ade,0x369d3864,0x379538fd,0x2f6c3449,0x304b34f1,0xb229a8f5,0xb31ea9be,0xb7b8b577,0xb868b649,0xb9d0b8e5,0xba79b987,0xbb36ba97,0xbbb6bb35,
0x3b013b86,0x3b8c3be7,0x39753a4f,0x3a193af0,0x36bc3878,0x37b3390f,0x2f91345e,0x305e3506,0xb247a90e,0xb33da9d7,0xb7dcb592,0xb879b663,0xb9e7b8fa,0xba8cb99a,0xbb4abaad,0xbbc2bb46,
0x3b153b96,0x3b993bee,0x398a3a65,0x3a2d3b02,0x36dc388b,0x37d13921,0x2fb63473,0x3071351b,0xb266a927,0xb35ca9f0,0xb800b5ac,0xb88ab67d,0xb9fdb90f,0xba9fb9ad,0xbb5cbac3,0xbbccbb56,
0x3b283ba5,0x3ba63bf4,0x39a03a7a,0x3a3f3b13,0x36fb389e,0x37ef3933,0x2fdc3488,0x30833530,0xb285a940,0xb37aaa09,0xb811b5c7,0xb89bb697,0xba12b924,0xbab1b9c0,0xbb6dbad7,0xbbd6bb65,
0x3b3b3bb3,0x3bb23bf9,0x39b53a8f,0x3a523b24,0x371a38b2,0x38073945,0x3001349d,0x30963545,0xb2a4a959,0xb399aa22,0xb823b5e1,0xb8abb6b1,0xba28b938,0xbac3b9d2,0xbb7ebaeb,0xbbdfbb74,
0x3b4d3bc0,0x3bbd3bfc,0x39ca3aa4,0x3a643b34,0x373938c5,0x38153957,0x301334b3,0x30a9355a,0xb2c2a972,0xb3b7aa3b,0xb834b5fb,0xb8bcb6ca,0xba3cb94c,0xbad4b9e4,0xbb8dbaff,0xbbe6bb82,
0x20e921b2,0x31313204,0x1ead2020,0x2f14305e,0x1b121d1b,0x2b822d6b,0xe4817db,0x1ead282c,0x997f94b6,0xa9d7a502,0x9de49c52,0xae40ac96,0xa0849f76,0xb0c8afe8,0xa216a14d,0xb26cb19b,
0x275d2845,0x31cc32b6,0x2502262f,0x2fe830e1,0x214d23a8,0x2c322e0e,0x14b61de4,0x1f7628aa,0xa0209b12,0xaa87a598,0xa46ba27b,0xaefbad20,0xa6c6a598,0xb156b06a,0xa890a7f3,0xb32bb241,
0x2a222b1d,0x32663368,0x282c2927,0x305e3163,0x246b2661,0x2ca22eb0,0x17db20e9,0x20202927,0xa2df9de4,0xab36a62f,0xa75da566,0xafb6adaa,0xa9a5a8aa,0xb1e5b0e1,0xab9baaa0,0xb3e8b2e7,
0x2c4b2cfa,0x3300340c,0x29d72b36,0x30c831e5,0x262f2877,0x2d132f53,0x197f22df,0x208429a5,0xa4cfa020,0xabe6a6c6,0xa927a78f,0xb039ae33,0xabe6aa87,0xb273b156,0xad52aca2,0xb452b38d,
0x2d842e65,0x33993464,0x2b822ca2,0x31313266,0x27f329be,0x2d842ff5,0x1b12246b,0x20e92a22,0xa62fa14d,0xac4ba75d,0xaaa0a8dc,0xb096aebd,0xad13ac32,0xb300b1cc,0xaed6adf5,0xb4b0b418,
0x2ebd2fcf,0x341834bc,0x2c962daa,0x319b32e7,0x28dc2b04,0x2df5304b,0x1c522566,0x214d2aa0,0xa78fa27b,0xaca2a7f3,0xac0ca9f0,0xb0f3af46,0xae33ad20,0xb38db241,0xb02caf46,0xb50cb46a,
0x2ff5309c,0x34643512,0x2d6b2eb0,0x32043368,0x29be2c25,0x2e65309c,0x1d1b2661,0x21b22b1d,0xa877a3a8,0xacfaa845,0xacc8ab04,0xb150afcf,0xaf53ae0e,0xb40cb2b6,0xb0edb04b,0xb568b4bc,
0x30963150,0x34b03568,0x2e402fb6,0x326c33e8,0x2aa02cc8,0x2ed630ed,0x1de4275d,0x22162b9b,0xa927a46b,0xad52a890,0xad84ac0c,0xb1adb02c,0xb039aefb,0xb452b32b,0xb1adb0f3,0xb5c4b50c,
0x34fa35be,0x373e3826,0x32d53434,0x35063627,0x2f46313e,0x316333bd,0x227b2c0c,0x24cf2e01,0xadaaa8dc,0xb032ab36,0xb20ab071,0xb473b291,0xb497b39f,0xb6b4b598,0xb61eb55d,0xb867b7c6,
0x35453612,0x3784384c,0x333d3473,0x35393663,0x2fb6318e,0x319b3406,0x22df2c4b,0x25022e40,0xae01a927,0xb05eab82,0xb266b0b5,0xb4a0b2d5,0xb4ddb409,0xb6f5b5cf,0xb678b5ac,0xb88fb808,
0x358f3666,0x37c93872,0x33a534b3,0x356b36a0,0x301331df,0x31d2342e,0x23442c89,0x25342e7e,0xae59a972,0xb08aabcd,0xb2c2b0f9,0xb4ceb318,0xb521b443,0xb736b607,0xb6d0b5fb,0xb8b7b82c,
0x35d836b9,0x38073898,0x340634f1,0x359d36dc,0x304b322f,0x320a3455,0x23a82cc8,0x25662ebd,0xaeb0a9be,0xb0b5ac0c,0xb31eb13e,0xb4fab35c,0xb565b47c,0xb776b63e,0xb728b649,0xb8deb850,
0x3621370c,0x382838bd,0x343a3530,0x35cf3717,0x3083327f,0x3241347c,0x24062d07,0x25982efb,0xaf08aa09,0xb0e1ac32,0xb37ab182,0xb527b39f,0xb5a9b4b6,0xb7b6b675,0xb77eb697,0xb904b874,
0x3669375d,0x384a38e1,0x346d356e,0x36013752,0x30bb32cf,0x327934a4,0x24392d45,0x25cb2f3a,0xaf5faa54,0xb10cac57,0xb3d6b1c6,0xb554b3e2,0xb5edb4ee,0xb7f5b6ab,0xb7d4b6e4,0xb92ab897,
0x36b137ad,0x386b3905,0x34a035ac,0x3632378c,0x30f3331e,0x32b034cb,0x246b2d84,0x25fd2f78,0xafb6aaa0,0xb137ac7d,0xb418b20a,0xb580b412,0xb62fb527,0xb81ab6e1,0xb814b730,0xb94eb8b9,
0x36f837fd,0x388b3928,0x34d435ea,0x366337c6,0x312b336e,0x32e734f1,0x249d2dc3,0x262f2fb6,0xb007aaeb,0xb163aca2,0xb446b24e,0xb5acb434,0xb672b55f,0xb838b717,0xb83eb77c,0xb972b8db,
0x38ab394b,0x399b3a45,0x36943800,0x380838db,0x331e3518,0x346a3649,0x26612ff5,0x27f330f3,0xb18eacc8,0xb2e7adf5,0xb5d8b455,0xb730b55d,0xb857b74c,0xb93eb874,0xb996b8fd,0xba91b9f3,
0x38cb396d,0x39b73a61,0x36c5381c,0x381f38f5,0x3356353f,0x3485366f,0x2694301a,0x28133112,0xb1b9acee,0xb312ae1a,0xb604b476,0xb75ab57d,0xb875b781,0xb959b88c,0xb9b8b91e,0xbaadba0f,
0x38ea398e,0x39d23a7c,0x36f53838,0x3836390f,0x338d3565,0x34a03694,0x26c63039,0x282c3131,0xb1e5ad13,0xb33dae40,0xb62fb497,0xb784b59d,0xb893b7b6,0xb974b8a5,0xb9dab93e,0xbac7ba2b,
0x390939ae,0x39ed3a97,0x37253854,0x384c3928,0x33c3358c,0x34bc36b9,0x26f83058,0x28453150,0xb210ad39,0xb368ae65,0xb65bb4b9,0xb7adb5be,0xb8b0b7ea,0xb98eb8bd,0xb9fbb95e,0xbae0ba45,
0x392739ce,0x3a073ab0,0x37553870,0x38633941,0x33fa35b2,0x34d736de,0x272a3077,0x285e316f,0xb23bad5e,0xb393ae8b,0xb686b4da,0xb7d7b5de,0xb8cdb80f,0xb9a8b8d5,0xba1bb97d,0xbaf9ba5f,
0x394539ed,0x3a213ac9,0x3784388b,0x3879395a,0x341835d8,0x34f13703,0x275d3096,0x2877318e,0xb266ad84,0xb3bdaeb0,0xb6b1b4fa,0xb800b5fe,0xb8eab828,0xb9c1b8ed,0xba3ab99b,0xbb10ba79,
0x39623a0b,0x3a3a3ae0,0x37b338a6,0x388f3972,0x343435fe,0x350c3728,0x278f30b5,0x289031ad,0xb291adaa,0xb3e8aed6,0xb6dcb51b,0xb814b61e,0xb906b842,0xb9dab904,0xba58b9b9,0xbb26ba91,
0x397f3a29,0x3a523af7,0x37e238c1,0x38a5398a,0x344f3624,0x3527374c,0x27c130d4,0x28aa31cc,0xb2bcadcf,0xb409aefb,0xb706b53c,0xb828b63e,0xb922b85b,0xb9f2b91b,0xba75b9d7,0xbb3cbaa9,
0x3a6a3b0d,0x3b113b9c,0x38bb39a2,0x39603a51,0x35423770,0x36153846,0x28c331eb,0x298c32e1,0xb41faf21,0xb4c8b026,0xb83cb65e,0xb8d7b757,0xba0ab932,0xbab8b9de,0xbb50bac0,0xbbcbbb5e,
0x3a813b22,0x3b243ba9,0x38d039b9,0x39743a65,0x355d3795,0x362f3857,0x28dc320a,0x29a53300,0xb434af46,0xb4ddb039,0xb850b67d,0xb8eab776,0xba22b949,0xbacbb9f2,0xbb63bad7,0xbbd6bb6e,
0x3a973b36,0x3b353bb6,0x38e539d0,0x39873a79,0x357737b8,0x36493868,0x28f53229,0x29be331e,0xb449af6c,0xb4f1b04b,0xb864b69d,0xb8fdb795,0xba39b95f,0xbadeba06,0xbb75baec,0xbbdfbb7d,
0x3aad3b4a,0x3b463bc2,0x38fa39e7,0x399a3a8c,0x359237dc,0x36633879,0x290e3247,0x29d7333d,0xb45eaf91,0xb506b05e,0xb878b6bc,0xb90fb7b3,0xba4fb975,0xbaf0ba19,0xbb86bb01,0xbbe7bb8c,
0x3ac33b5c,0x3b563bcc,0x390f39fd,0x39ad3a9f,0x35ac3800,0x367d388a,0x29273266,0x29f0335c,0xb473afb6,0xb51bb071,0xb88bb6dc,0xb921b7d1,0xba65b98a,0xbb02ba2d,0xbb96bb15,0xbbeebb99,
0x3ad73b6d,0x3b653bd6,0x39243a12,0x39c03ab1,0x35c73811,0x3697389b,0x29403285,0x2a09337a,0xb488afdc,0xb530b083,0xb89eb6fb,0xb933b7ef,0xba7ab9a0,0xbb13ba3f,0xbba5bb28,0xbbf4bba6,
0x3aeb3b7e,0x3b743bdf,0x39383a28,0x39d23ac3,0x35e13823,0x36b138ab,0x295932a4,0x2a223399,0xb49db001,0xb545b096,0xb8b2b71a,0xb945b807,0xba8fb9b5,0xbb24ba52,0xbbb3bb3b,0xbbf9bbb2,
0x3aff3b8d,0x3b823be6,0x394c3a3c,0x39e43ad4,0x35fb3834,0x36ca38bc,0x297232c2,0x2a3b33b7,0xb4b3b013,0xb55ab0a9,0xb8c5b739,0xb957b815,0xbaa4b9ca,0xbb34ba64,0xbbc0bb4d,0xbbfcbbbd,
0x39b839ba,0x3a973ab5,0x39b339b5,0x3a583a78,0x39af39b1,0x3a153a37,0x39aa39ad,0x39cd39f2,0x39a639a8,0x398239a8,0x39a139a4,0x3933395b,0x399d399f,0x38e03909,0x3999399b,0x388938b5,
0xb979b972,0xb865b832,0xb986b980,0xb8c7b896,0xb994b98d,0xb924b8f6,0xb9a1b99b,0xb97db951,0xb9afb9a8,0xb9d2b9a8,0xb9bcb9b5,0xba21b9fa,0xb9c9b9c3,0xba6bba47,0xb9d6b9d0,0xbab0ba8e,
0xb9f4b9fe,0xbac7bae9,0xb9dfb9e9,0xba7ebaa3,0xb9c9b9d4,0xba2dba56,0xb9b3b9be,0xb9d6ba02,0xb99db9a8,0xb979b9a8,0xb986b992,0xb916b948,0xb970b97b,0xb8adb8e2,0xb958b964,0xb840b877,
0x39373927,0x381a37b7,0x39583948,0x38943858,0x39793969,0x390738ce,0x39993989,0x3974393e,0x39b839a8,0x39da39a8,0x39d639c7,0x3a393a0b,0x39f439e5,0x3a903a65,0x3a113a02,0x3ade3ab8,
0x3a2d3a3f,0x3af43b1a,0x3a093a1b,0x3aa23acc,0x39e339f6,0x3a453a74,0x39bc39d0,0x39df3a13,0x399439a8,0x397039a8,0x396b3980,0x38f83935,0x39413956,0x387a38ba,0x3916392b,0x37e83838,
0xb8f3b8d8,0xb79bb705,0xb929b90e,0xb85fb817,0xb95db943,0xb8eab8a6,0xb990b976,0xb96bb92b,0xb9c0b9a8,0xb9e3b9a8,0xb9f0b9d8,0xba50ba1b,0xba1dba07,0xbab3ba83,0xba49ba33,0xbb0abae0,
0xba64ba7c,0xbb1ebb46,0xba31ba4b,0xbac4baf3,0xb9fcba17,0xba5cba92,0xb9c5b9e1,0xb9e7ba23,0xb98bb9a8,0xb966b9a8,0xb94fb96d,0xb8dbb922,0xb911b930,0xb845b891,0xb8d1b8f1,0xb74eb7ee,
0x38ad3887,0x36ff364e,0x38f838d3,0x382a37ac,0x3941391d,0x38cc387c,0x39863964,0x39623918,0x39c939a8,0x39eb39a8,0x3a0939e9,0x3a673a2b,0x3a453a27,0x3ad53aa0,0x3a7e3a62,0x3b323b05,
0x3b453b6e,0x3bbc3bdd,0x3ae53b17,0x3b573b8f,0x3a733aae,0x3ac73b14,0x39f03a33,0x3a113a71,0x395d39a8,0x393739a8,0x38bc390e,0x384038bf,0x380f3867,0x365f3775,0x36af376a,0x341a3540,
0xb65fb593,0xb389b115,0xb7e8b726,0xb625b4f9,0xb8adb852,0xb830b748,0xb958b905,0xb933b8b5,0xb9f4b9a8,0xba15b9a8,0xba7eba3b,0xbad1ba78,0xbaf4babc,0xbb63bb20,0xbb57bb28,0xbbc6bb9b,
0xbb68bb91,0xbbd0bbed,0xbb04bb39,0xbb6fbba6,0xba89bac9,0xbadbbb2b,0xb9f8ba43,0xba19ba7f,0xb954b9a8,0xb92eb9a8,0xb89eb8fb,0xb820b8ab,0xb7b2b83d,0xb5ebb71b,0xb60eb6e3,0xb2deb4b1,
0x35bc34d5,0x32322f0e,0x377a369e,0x35b13469,0x388e3828,0x380f36ee,0x394f38f1,0x392938a0,0x39fc39a8,0x3a1d39a8,0x3a933a4b,0x3ae53a87,0x3b133ad6,0x3b7a3b36,0x3b783b49,0x3bd93bb1,
0x3b873baf,0x3be13bf8,0x3b213b58,0x3b853bbb,0x3a9e3ae3,0x3aee3b41,0x3a003a52,0x3a213a8e,0x394a39a8,0x392439a8,0x387f38e7,0x37fe3896,0x37423812,0x357636c1,0x356a3659,0x31853420,
0xb517b414,0xb0d7abd9,0xb70ab614,0xb53ab3ae,0xb86fb7f9,0xb7ddb693,0xb946b8dd,0xb91fb88c,0xba04b9a8,0xba25b9a8,0xbaa9ba5a,0xbaf7ba95,0xbb2fbaf0,0xbb90bb4b,0xbb96bb67,0xbbe8bbc4,
0xbba3bbc9,0xbbefbbff,0xbb3dbb74,0xbb9abbcd,0xbab3bafc,0xbb01bb55,0xba09ba62,0xba29ba9c,0xb941b9a8,0xb91bb9a8,0xb85fb8d3,0xb7bdb881,0xb6d2b7cd,0xb4ffb665,0xb4c3b5ce,0xb029b31b,
0x346f32a1,0x2ef52248,0x36993587,0x34c33288,0x385037a1,0x379b3637,0x393c38c9,0x39163877,0x3a0d39a8,0x3a2d39a8,0x3abd3a69,0x3b0a3aa3,0x3b4a3b08,0x3ba33b5f,0x3bb03b82,0x3bf43bd5,
0x3bf83c00,0x3bf93bd4,0x3bac3bdc,0x3be43bfe,0x3b133b69,0x3b543bab,0x3a313aaa,0x3a503ae0,0x391139a8,0x38ea39a8,0x377a386d,0x366b3817,0x34873608,0x313b348d,0x2d9731f4,0xad65291b,
0xac3828b6,0x2ec33365,0xb44bb160,0xb0bea57f,0xb759b5da,0xb648b45d,0xb90cb862,0xb8e5b80d,0xba35b9a8,0xba54b9a8,0xbb1bbab1,0xbb5cbae6,0xbbb5bb72,0xbbe9bbb2,0xbbfcbbe3,0xbbf5bc00,
0xbbfebbfc,0xbbefbbbc,0xbbbdbbe9,0xbbeebc00,0xbb24bb7b,0xbb63bbb9,0xba39bab8,0xba58baed,0xb907b9a8,0xb8e0b9a8,0xb737b858,0xb625b802,0xb40eb5ab,0xb042b42c,0xa9b1b0cb,0x30109a48,
0x25e4ad7e,0xb0beb475,0x33a23036,0x2f8ba3db,0x3715357c,0x360233f7,0x3902384d,0x38db37ee,0x3a3d39a8,0x3a5c39a8,0x3b2c3abf,0x3b6a3af3,0x3bc53b84,0x3bf23bc0,0x3bff3bee,0x3be93c00,
0x3c003bf4,0x3be23ba0,0x3bcc3bf3,0x3bf53bff,0x3b353b8c,0x3b713bc6,0x3a413ac6,0x3a603af9,0x38fd39a8,0x38d639a8,0x36f43842,0x35df37d8,0x3328354c,0x2e913396,0x16482f40,0xb16ca852,
0x251b304e,0x32193534,0xb2adae14,0xad972aac,0xb6d2b51d,0xb5bcb334,0xb8f8b838,0xb8d1b7c2,0xba45b9a8,0xba64b9a8,0xbb3dbacc,0xbb78baff,0xbbd3bb95,0xbbf8bbcb,0xbc00bbf7,0xbbdabbfd,
0xbbfebbe6,0xbbd2bb80,0xbbd9bbfa,0xbbfbbbfb,0xbb45bb9d,0xbb7fbbd1,0xba49bad3,0xba67bb05,0xb8f3b9a8,0xb8ccb9a8,0xb6afb82d,0xb599b7ac,0xb232b4ed,0xac9cb2d2,0x294dace7,0x32c62c83,
0xac06b1db,0xb371b5f1,0x31b62b75,0x2b43adb0,0x368d34bd,0x3576326f,0x38ee3822,0x38c73796,0x3a4d39a8,0x3a6b39a8,0x3b4c3ad9,0x3b853b0b,0x3bdf3ba4,0x3bfd3bd6,0x3bfc3bfd,0x3bc83bf8,
0x3bbd3b5a,0x3b473a99,0x3bfe3bf4,0x3bf93bbe,0x3b8b3bdb,0x3bb83bf7,0x3a6f3b11,0x3a8c3b3e,0x38c139a8,0x389939a8,0x35523780,0x343236cc,0x294d320d,0xad332de2,0xb40eaedc,0xb6a4b408,
0x346336aa,0x36f438b0,0xa6ad3004,0x2e2d3451,0xb52fb1aa,0xb40ead1a,0xb8bcb76a,0xb894b6b5,0xba73b9a8,0xba90b9a8,0xbb92bb17,0xbbbdbb43,0xbbffbbe0,0xbbf6bbf9,0xbbb2bbf0,0xbb35bbb4,
0xbba5bb30,0xbb21ba5e,0xbc00bbeb,0xbbf3bbaa,0xbb98bbe4,0xbbc2bbfb,0xba76bb1d,0xba93bb49,0xb8b7b9a8,0xb88eb9a8,0xb50bb753,0xb3d3b69e,0xa17fb147,0x2f27ac51,0x34b73099,0x37423499,
0xb50bb75e,0xb790b900,0x9cb6b12e,0xb010b4e1,0x34e730e4,0x33892b11,0x38b2373d,0x38893687,0x3a7a39a8,0x3a9739a8,0x3b9e3b22,0x3bc63b4e,0x3c003be8,0x3bef3bfd,0x3b983be5,0x3b0d3b9e,
0x3b893b02,0x3af73a1f,0x3c003bdf,0x3beb3b93,0x3ba33bec,0x3bcb3bfe,0x3a7e3b28,0x3a9b3b53,0x38ad39a8,0x388439a8,0x34c33726,0x33403670,0xa51b3080,0xb08d297f,0xb55eb1c3,0xb7ddb529,
0x35b13807,0x3815394d,0x28843257,0x31093570,0xb49fb01d,0xb2f7a7da,0xb8a8b710,0xb87fb659,0xba81b9a8,0xba9eb9a8,0xbba9bb2e,0xbbcfbb58,0xbbffbbef,0xbbe6bbff,0xbb7abbd7,0xbae1bb86,
0xbb6abad0,0xbacbb9dc,0xbbfdbbd0,0xbbe1bb79,0xbbaebbf2,0xbbd3bc00,0xba85bb33,0xbaa2bb5d,0xb8a3b9a8,0xb87ab9a8,0xb47bb6f9,0xb2adb642,0x2a7aaf72,0x3185a4b6,0x360232ea,0x383a35b6,
0xb654b85d,0xb85fb996,0xac38b37d,0xb201b5fd,0x34572eaa,0x32631e48,0x389e36e3,0x3874362b,0x3a8939a8,0x3aa539a8,0x3bb33b39,0x3bd73b62,0x3bfc3bf5,0x3bdc3c00,0x3b593bc7,0x3ab33b6b,
0x39b739b9,0x3a883aa6,0x39b239b4,0x3a483a68,0x39ae39b0,0x3a033a26,0x39a939ab,0x39bb39e0,0x39a539a7,0x396e3995,0x39a039a3,0x391e3947,0x399c399e,0x38ca38f5,0x3997399a,0x3873389f,
0xb97cb975,0xb87eb84c,0xb98ab983,0xb8deb8ae,0xb997b991,0xb93bb90d,0xb9a5b99e,0xb993b967,0xb9b2b9ab,0xb9e6b9bd,0xb9bfb9b9,0xba34ba0e,0xb9ccb9c6,0xba7dba59,0xb9d9b9d3,0xbac0ba9f,
0xb9efb9f9,0xbab6bad9,0xb9d9b9e4,0xba6aba91,0xb9c4b9cf,0xba18ba42,0xb9aeb9b9,0xb9bfb9ec,0xb997b9a3,0xb961b991,0xb981b98c,0xb8fcb92f,0xb96ab975,0xb892b8c8,0xb953b95e,0xb824b85c,
0x3940392f,0x383937f6,0x39613950,0x38b13876,0x39813971,0x392338eb,0x39a03991,0x398e395a,0x39bf39b0,0x39f339c1,0x39de39cf,0x3a4f3a22,0x39fb39ec,0x3aa43a7b,0x3a183a0a,0x3af03acb,
0x3a243a36,0x3ae13b07,0x39ff3a12,0x3a8b3ab7,0x39d939ec,0x3a2c3a5d,0x39b239c6,0x39c439f9,0x398a399e,0x3953398c,0x39613975,0x38d93917,0x3936394b,0x3859389a,0x390b3921,0x37a43816,
0xb901b8e6,0xb7e6b750,0xb936b91c,0xb883b83c,0xb96ab950,0xb90bb8c8,0xb99cb983,0xb98ab94b,0xb9ccb9b4,0xb9ffb9c6,0xb9fbb9e4,0xba6aba36,0xba28ba12,0xbacaba9b,0xba53ba3e,0xbb1dbaf5,
0xba57ba70,0xbb09bb33,0xba24ba3e,0xbaabbadc,0xb9efba0a,0xba40ba77,0xb9b7b9d3,0xb9c8ba05,0xb97cb99a,0xb944b988,0xb940b95e,0xb8b6b8fe,0xb901b921,0xb81eb86b,0xb8c0b8e1,0xb6fcb79e,
0x38c0389a,0x375636a7,0x390b38e6,0x38543800,0x3953392f,0x38f238a4,0x39973975,0x3985393d,0x39d939b9,0x3a0c39ca,0x3a1839f9,0x3a843a4a,0x3a533a36,0x3aed3abb,0x3a8b3a70,0x3b473b1c,
0x3b2e3b5a,0x3ba63bce,0x3aca3afe,0x3b373b74,0x3a533a91,0x3a9d3aef,0x39cc3a12,0x39de3a42,0x39363983,0x38fc3971,0x389238e6,0x37fb3880,0x37c5383c,0x35d136eb,0x3651370d,0x330934ae,
0xb6c3b5fa,0xb460b251,0xb824b788,0xb6b8b590,0xb8d9b880,0xb873b7d5,0xb981b92f,0xb96eb8f5,0xba18b9cf,0xba48b9e0,0xba9dba5d,0xbafabaa6,0xbb0fbad9,0xbb80bb43,0xbb6cbb40,0xbbd8bbb2,
0xbb51bb7d,0xbbbdbbe0,0xbae7bb1f,0xbb4ebb8c,0xba66baa9,0xbaafbb04,0xb9d1ba1e,0xb9e2ba4e,0xb928b97e,0xb8edb96c,0xb86eb8cd,0xb7afb866,0xb74bb80b,0xb54fb684,0xb5a2b679,0xb197b411,
0x362e3549,0x338330de,0x37e6370d,0x3651350e,0x38c0385c,0x38593788,0x397c3921,0x396a38e6,0x3a2439d3,0x3a5339e4,0x3ab63a70,0x3b0f3ab7,0x3b2e3af5,0x3b973b5a,0x3b8d3b61,0x3be83bc7,
0x3b703b9c,0x3bd03bef,0x3b033b3d,0x3b653ba2,0x3a793ac1,0x3ac03b19,0x39d53a2a,0x39e63a59,0x3919397a,0x38de3967,0x384938b4,0x3761384c,0x36cf37b4,0x34cc361d,0x34f035e2,0x302332e4,
0xb596b496,0xb244aecf,0xb783b690,0xb5e8b48a,0xb8a7b836,0xb83eb73a,0xb978b912,0xb965b8d7,0xba30b9d7,0xba5fb9e8,0xbacdba82,0xbb23bac8,0xbb4cbb10,0xbbacbb6f,0xbbaabb7f,0xbbf4bbd8,
0xbb8dbbb7,0xbbe0bbf9,0xbb1dbb5a,0xbb7abbb5,0xba8bbad9,0xbad0bb2d,0xb9d9ba36,0xb9eaba65,0xb90bb975,0xb8cfb963,0xb824b89a,0xb713b831,0xb651b750,0xb447b5b3,0xb43bb549,0xad58b1a4,
0x34fc33c0,0x31032bc0,0x371e3611,0x357e3405,0x388d3811,0x382436eb,0x39733903,0x396138c8,0x3a3c39db,0x3a6a39ec,0x3ae43a94,0x3b373ad9,0x3b673b2a,0x3bbe3b83,0x3bc33b9a,0x3bfc3be7,
0x3bed3bff,0x3bff3bea,0x3b8d3bc7,0x3bcc3bf5,0x3ae13b40,0x3b1d3b83,0x39ef3a70,0x39ff3a9b,0x38c0395e,0x3883394b,0x36c33816,0x357e3750,0x33833549,0x2e84332e,0x28cf3061,0xb0aca5b2,
0xaf7ea376,0x29663166,0xb514b2fd,0xb2bfad71,0xb809b69b,0xb734b555,0xb95cb8b9,0xb949b87b,0xba75b9f1,0xbaa1ba01,0xbb49bae9,0xbb8bbb25,0xbbcfbb96,0xbbf9bbd2,0xbc00bbf2,0xbbe3bbfe,
0xbbf6bc00,0xbbfcbbda,0xbb9fbbd6,0xbbd8bbfb,0xbaf0bb52,0xbb2cbb92,0xb9f3ba7b,0xba03baa6,0xb8b1b95a,0xb873b947,0xb673b7f6,0xb52cb718,0xb276b4de,0xac5eb251,0x2052ae39,0x321f2bf2,
0x2cf4a806,0xad3fb2d8,0x34a831ee,0x31e22a93,0x37db364b,0x36fc3502,0x395738a9,0x3944386b,0x3a8039f5,0x3aab3a05,0x3b5b3af8,0x3b993b33,0x3bdd3ba7,0x3bfd3bdd,0x3bff3bfa,0x3bd13bf9,
0x3bfd3bfd,0x3bf53bc6,0x3baf3be3,0x3be23bff,0x3b003b64,0x3b393ba0,0x39f73a86,0x3a083ab0,0x38a23955,0x38633942,0x362237bf,0x34d836e0,0x31663472,0x286b3172,0xaaf82b5c,0xb390ae84,
0xa8cf2cf4,0x2fc93423,0xb43bb0de,0xb103a484,0xb7a4b5fa,0xb6c3b4ae,0xb953b89a,0xb940b85c,0xba8bb9f9,0xbab6ba0a,0xbb6cbb07,0xbba6bb40,0xbbe8bbb7,0xbc00bbe7,0xbbfabbff,0xbbbabbf1,
0xbc00bbf6,0xbbebbbae,0xbbbebbed,0xbbebbc00,0xbb0fbb74,0xbb47bbad,0xb9fbba91,0xba0cbabb,0xb892b950,0xb854b93d,0xb5d1b788,0xb484b6a7,0xb055b405,0x9248b093,0x2e6ba484,0x347e3086,
0x98b6afe2,0xb128b4d8,0x339c2f97,0x3023a420,0x376c35a8,0x368a345a,0x394e388b,0x393b384c,0x3a9639fd,0x3ac03a0e,0x3b7c3b16,0x3bb33b4d,0x3bf23bc5,0x3c003bef,0x3bf03c00,0x3ba03be5,
0x3bde3b91,0x3b8a3af7,0x3bf23bff,0x3c003be3,0x3b533bb9,0x3b823bdf,0x3a103ac5,0x3a203aec,0x38443939,0x38033925,0x342f366d,0x31b03584,0xa8392f65,0xb15a1d7f,0xb531b1c9,0xb7e0b55b,
0x3269358a,0x35a83819,0xae842a61,0x205231e2,0xb651b405,0xb567b15a,0xb936b83c,0xb923b7f6,0xbacaba12,0xbaf0ba22,0xbbbebb5a,0xbbe3bb88,0xbbfdbbf5,0xbbddbc00,0xbb81bbd6,0xbadfbb7c,
0xbbcebb70,0xbb6dbac6,0xbbf8bbfb,0xbbffbbd6,0xbb60bbc4,0xbb8dbbe7,0xba14bacf,0xba24baf5,0xb834b934,0xb7e6b921,0xb3b4b634,0xb103b549,0x2c44ada3,0x326925b2,0x35e23309,0x384135f4,
0xb3a8b63a,0xb63fb869,0x2cc2ad58,0xa89db2f0,0x3617335f,0x352c30ac,0x3931382c,0x391e37d5,0x3ad43a16,0x3afa3a26,0x3bc93b66,0x3bea3b92,0x3bf93bfa,0x3bcf3bff,0x3b5f3bc5,0x3aad3b5d,
0x3bba3b4c,0x3b4d3a93,0x3bfc3bf6,0x3bfd3bc7,0x3b6c3bce,0x3b973bed,0x3a183ad9,0x3a283afe,0x3824392f,0x37c5391c,0x330935fa,0x3055350e,0xae6b2bc0,0xb377aa61,0xb690b423,0xb890b68a,
0x347236e5,0x36d438b6,0xa9fd2f7e,0x2c1233fd,0xb5dcb2b3,0xb4f0affb,0xb92db81c,0xb919b7b4,0xbaddba1a,0xbb03ba2a,0xbbd3bb72,0xbbf0bb9c,0xbbf2bbfe,0xbbbfbbfc,0xbb38bbaf,0xba77bb3c,
0xbba4bb23,0xbb2aba5b,0xbbffbbee,0xbbfabbb6,0xbb77bbd7,0xbba1bbf3,0xba1cbae2,0xba2cbb07,0xb813b92a,0xb7a4b917,0xb25db5bf,0xaf4cb4d2,0x3048a839,0x34412cf4,0x373a34c0,0x38dc371e,
0xb50eb78e,0xb767b901,0x24e9b0d1,0xadd5b484,0x35a23207,0x34b42e9d,0x3928380b,0x39143793,0x3ae73a1e,0x3b0c3a2e,0x3bdb3b7d,0x3bf53ba6,0x3be93c00,0x3bad3bf7,0x3b0d3b97,0x3a3e3b18,
0xb999b996,0xb889b85d,0xb99db99b,0xb8e0b8b5,0xb9a1b99f,0xb933b909,0xb9a6b9a4,0xb982b95b,0xb9aab9a8,0xb9cdb9a8,0xb9afb9ad,0xba15b9f2,0xb9b3b9b1,0xba58ba37,0xb9b8b9b5,0xba97ba78,
0xb9d6b9dc,0xbab0bad0,0xb9c9b9d0,0xba6bba8e,0xb9bcb9c3,0xba21ba47,0xb9afb9b5,0xb9d2b9fa,0xb9a1b9a8,0xb97db9a8,0xb994b99b,0xb924b951,0xb986b98d,0xb8c7b8f6,0xb979b980,0xb865b896,
0x3958394d,0x38403807,0x39703964,0x38ad3877,0x3986397b,0x391638e2,0x399d3992,0x39793948,0x39b339a8,0x39d639a8,0x39c939be,0x3a2d3a02,0x39df39d4,0x3a7e3a56,0x39f439e9,0x3ac73aa3,
0x3a113a1f,0x3ade3b02,0x39f43a02,0x3a903ab8,0x39d639e5,0x3a393a65,0x39b839c7,0x39da3a0b,0x399939a8,0x397439a8,0x39793989,0x3907393e,0x39583969,0x389438ce,0x39373948,0x381a3858,
0xb916b900,0xb7e8b75e,0xb941b92b,0xb87ab838,0xb96bb956,0xb8f8b8ba,0xb994b980,0xb970b935,0xb9bcb9a8,0xb9dfb9a8,0xb9e3b9d0,0xba45ba13,0xba09b9f6,0xbaa2ba74,0xba2dba1b,0xbaf4bacc,
0xba49ba5e,0xbb0abb30,0xba1dba33,0xbab3bae0,0xb9f0ba07,0xba50ba83,0xb9c0b9d8,0xb9e3ba1b,0xb990b9a8,0xb96bb9a8,0xb95db976,0xb8eab92b,0xb929b943,0xb85fb8a6,0xb8f3b90e,0xb79bb817,
0x38d138b0,0x374e36aa,0x391138f1,0x384537ee,0x394f3930,0x38db3891,0x398b396d,0x39663922,0x39c539a8,0x39e739a8,0x39fc39e1,0x3a5c3a23,0x3a313a17,0x3ac43a92,0x3a643a4b,0x3b1e3af3,
0x3a7e3a99,0x3b323b5a,0x3a453a62,0x3ad53b05,0x3a093a27,0x3a673aa0,0x39c939e9,0x39eb3a2b,0x398639a8,0x396239a8,0x39413964,0x38cc3918,0x38f8391d,0x382a387c,0x38ad38d3,0x36ff37ac,
0xb6afb5f1,0xb41ab1db,0xb80fb76a,0xb65fb540,0xb8bcb867,0xb840b775,0xb95db90e,0xb937b8bf,0xb9f0b9a8,0xba11b9a8,0xba73ba33,0xbac7ba71,0xbae5baae,0xbb57bb14,0xbb45bb17,0xbbbcbb8f,
0xbb57bb80,0xbbc6bbe6,0xbaf4bb28,0xbb63bb9b,0xba7ebabc,0xbad1bb20,0xb9f4ba3b,0xba15ba78,0xb958b9a8,0xb933b9a8,0xb8adb905,0xb830b8b5,0xb7e8b852,0xb625b748,0xb65fb726,0xb389b4f9,
0x360e3534,0x32de304e,0x37b236e3,0x35eb34b1,0x389e383d,0x3820371b,0x395438fb,0x392e38ab,0x39f839a8,0x3a1939a8,0x3a893a43,0x3adb3a7f,0x3b043ac9,0x3b6f3b2b,0x3b683b39,0x3bd03ba6,
0x3b783ba0,0x3bd93bf4,0x3b133b49,0x3b7a3bb1,0x3a933ad6,0x3ae53b36,0x39fc3a4b,0x3a1d3a87,0x394f39a8,0x392939a8,0x388e38f1,0x380f38a0,0x377a3828,0x35b136ee,0x35bc369e,0x32323469,
0xb56ab475,0xb185ad7e,0xb742b659,0xb576b420,0xb87fb812,0xb7feb6c1,0xb94ab8e7,0xb924b896,0xba00b9a8,0xba21b9a8,0xba9eba52,0xbaeeba8e,0xbb21bae3,0xbb85bb41,0xbb87bb58,0xbbe1bbbb,
0xbb96bbbc,0xbbe8bbfc,0xbb2fbb67,0xbb90bbc4,0xbaa9baf0,0xbaf7bb4b,0xba04ba5a,0xba25ba95,0xb946b9a8,0xb91fb9a8,0xb86fb8dd,0xb7ddb88c,0xb70ab7f9,0xb53ab693,0xb517b614,0xb0d7b3ae,
0x34c33365,0x302928b6,0x36d235ce,0x34ff331b,0x385f37cd,0x37bd3665,0x394138d3,0x391b3881,0x3a0939a8,0x3a2939a8,0x3ab33a62,0x3b013a9c,0x3b3d3afc,0x3b9a3b55,0x3ba33b74,0x3bef3bcd,
0x3bb03bd4,0x3bf43c00,0x3b4a3b82,0x3ba33bd5,0x3abd3b08,0x3b0a3b5f,0x3a0d3a69,0x3a2d3aa3,0x393c39a8,0x391639a8,0x385038c9,0x379b3877,0x369937a1,0x34c33637,0x346f3587,0x2ef53288,
0xad972248,0x2d6532a1,0xb487b1f4,0xb13ba91b,0xb77ab608,0xb66bb48d,0xb911b86d,0xb8eab817,0xba31b9a8,0xba50b9a8,0xbb13baaa,0xbb54bae0,0xbbacbb69,0xbbe4bbab,0xbbf8bbdc,0xbbf9bbfe,
0xbbfcbbff,0xbbf5bbc9,0xbbb5bbe3,0xbbe9bc00,0xbb1bbb72,0xbb5cbbb2,0xba35bab1,0xba54bae6,0xb90cb9a8,0xb8e5b9a8,0xb759b862,0xb648b80d,0xb44bb5da,0xb0beb45d,0xac38b160,0x2ec3a57f,
0x29b1abd9,0xb010b414,0x340e30cb,0x30421a48,0x373735ab,0x3625342c,0x39073858,0x38e03802,0x3a3939a8,0x3a5839a8,0x3b243ab8,0x3b633aed,0x3bbd3b7b,0x3bee3bb9,0x3bfe3be9,0x3bef3c00,
0x3bff3bf8,0x3be93baf,0x3bc53bee,0x3bf23c00,0x3b2c3b84,0x3b6a3bc0,0x3a3d3abf,0x3a5c3af3,0x390239a8,0x38db39a8,0x3715384d,0x360237ee,0x33a2357c,0x2f8b33f7,0x25e43036,0xb0bea3db,
0x96482f0e,0x316c34d5,0xb328af40,0xae912852,0xb6f4b54c,0xb5dfb396,0xb8fdb842,0xb8d6b7d8,0xba41b9a8,0xba60b9a8,0xbb35bac6,0xbb71baf9,0xbbccbb8c,0xbbf5bbc6,0xbc00bbf3,0xbbe2bbff,
0xbc00bbed,0xbbdabb91,0xbbd3bbf7,0xbbf8bbfd,0xbb3dbb95,0xbb78bbcb,0xba45bacc,0xba64baff,0xb8f8b9a8,0xb8d1b9a8,0xb6d2b838,0xb5bcb7c2,0xb2adb51d,0xad97b334,0x251bae14,0x32192aac,
0xa94db115,0xb2c6b593,0x32322ce7,0x2c9cac83,0x36af34ed,0x359932d2,0x38f3382d,0x38cc37ac,0x3a4939a8,0x3a6739a8,0x3b453ad3,0x3b7f3b05,0x3bd93b9d,0x3bfb3bd1,0x3bfe3bfa,0x3bd23bfb,
0x3bfc3bdd,0x3bc83b6e,0x3bdf3bfd,0x3bfd3bf8,0x3b4c3ba4,0x3b853bd6,0x3a4d3ad9,0x3a6b3b0b,0x38ee39a8,0x38c739a8,0x368d3822,0x35763796,0x31b634bd,0x2b43326f,0xac062b75,0xb371adb0,
0x340e364e,0x36a43887,0xa94d2edc,0x2d333408,0xb552b20d,0xb432ade2,0xb8c1b780,0xb899b6cc,0xba6fb9a8,0xba8cb9a8,0xbb8bbb11,0xbbb8bb3e,0xbbfebbdb,0xbbf9bbf7,0xbbbdbbf4,0xbb47bbbe,
0xbbb2bb46,0xbb35ba7c,0xbbffbbf0,0xbbf6bbb4,0xbb92bbe0,0xbbbdbbf9,0xba73bb17,0xba90bb43,0xb8bcb9a8,0xb894b9a8,0xb52fb76a,0xb40eb6b5,0xa6adb1aa,0x2e2dad1a,0x34633004,0x36f43451,
0xb4b7b705,0xb742b8d8,0x217fb099,0xaf27b499,0x350b3147,0x33d32c51,0x38b73753,0x388e369e,0x3a7639a8,0x3a9339a8,0x3b983b1d,0x3bc23b49,0x3c003be4,0x3bf33bfb,0x3ba53beb,0x3b213baa,
0x3b983b1a,0x3b0d3a3f,0x3c003be5,0x3bef3b9e,0x3b9e3be8,0x3bc63bfd,0x3a7a3b22,0x3a973b4e,0x38b239a8,0x388939a8,0x34e7373d,0x33893687,0x9cb630e4,0xb0102b11,0xb50bb12e,0xb790b4e1,
0x355e37b7,0x37dd3927,0x251b31c3,0x308d3529,0xb4c3b080,0xb340a97f,0xb8adb726,0xb884b670,0xba7eb9a8,0xba9bb9a8,0xbba3bb28,0xbbcbbb53,0xbc00bbec,0xbbebbbfe,0xbb89bbdf,0xbaf7bb93,
0xbb7abae9,0xbae1b9fe,0xbbffbbd7,0xbbe6bb86,0xbba9bbef,0xbbcfbbff,0xba81bb2e,0xba9ebb58,0xb8a8b9a8,0xb87fb9a8,0xb49fb710,0xb2f7b659,0x2884b01d,0x3109a7da,0x35b13257,0x38153570,
0xb602b832,0xb83ab972,0xaa7ab2ea,0xb185b5b6,0x347b2f72,0x32ad24b6,0x38a336f9,0x387a3642,0x3a8539a8,0x3aa239a8,0x3bae3b33,0x3bd33b5d,0x3bfd3bf2,0x3be13c00,0x3b6a3bd0,0x3acb3b79,
0x3b593ab5,0x3ab339ba,0x3bfc3bc7,0x3bdc3b6b,0x3bb33bf5,0x3bd73c00,0x3a893b39,0x3aa53b62,0x389e39a8,0x387439a8,0x345736e3,0x3263362b,0xac382eaa,0xb2011e48,0xb654b37d,0xb85fb5fd,
0xb99ab997,0xb89fb873,0xb99eb99c,0xb8f5b8ca,0xb9a3b9a0,0xb947b91e,0xb9a7b9a5,0xb995b96e,0xb9abb9a9,0xb9e0b9bb,0xb9b0b9ae,0xba26ba03,0xb9b4b9b2,0xba68ba48,0xb9b9b9b7,0xbaa6ba88,
0xb9d3b9d9,0xba9fbac0,0xb9c6b9cc,0xba59ba7d,0xb9b9b9bf,0xba0eba34,0xb9abb9b2,0xb9bdb9e6,0xb99eb9a5,0xb967b993,0xb991b997,0xb90db93b,0xb983b98a,0xb8aeb8de,0xb975b97c,0xb84cb87e,
0x395e3953,0x385c3824,0x3975396a,0x38c83892,0x398c3981,0x392f38fc,0x39a33997,0x39913961,0x39b939ae,0x39ec39bf,0x39cf39c4,0x3a423a18,0x39e439d9,0x3a913a6a,0x39f939ef,0x3ad93ab6,
0x3a0a3a18,0x3acb3af0,0x39ec39fb,0x3a7b3aa4,0x39cf39de,0x3a223a4f,0x39b039bf,0x39c139f3,0x399139a0,0x395a398e,0x39713981,0x38eb3923,0x39503961,0x387638b1,0x392f3940,0x37f63839,
0xb921b90b,0xb816b7a4,0xb94bb936,0xb89ab859,0xb975b961,0xb917b8d9,0xb99eb98a,0xb98cb953,0xb9c6b9b2,0xb9f9b9c4,0xb9ecb9d9,0xba5dba2c,0xba12b9ff,0xbab7ba8b,0xba36ba24,0xbb07bae1,
0xba3eba53,0xbaf5bb1d,0xba12ba28,0xba9bbaca,0xb9e4b9fb,0xba36ba6a,0xb9b4b9cc,0xb9c6b9ff,0xb983b99c,0xb94bb98a,0xb950b96a,0xb8c8b90b,0xb91cb936,0xb83cb883,0xb8e6b901,0xb750b7e6,
0x38e138c0,0x379e36fc,0x39213901,0x386b381e,0x395e3940,0x38fe38b6,0x399a397c,0x39883944,0x39d339b7,0x3a0539c8,0x3a0a39ef,0x3a773a40,0x3a3e3a24,0x3adc3aab,0x3a703a57,0x3b333b09,
0x3a703a8b,0x3b1c3b47,0x3a363a53,0x3abb3aed,0x39f93a18,0x3a4a3a84,0x39b939d9,0x39ca3a0c,0x39753997,0x393d3985,0x392f3953,0x38a438f2,0x38e6390b,0x38003854,0x389a38c0,0x36a73756,
0xb70db651,0xb4aeb309,0xb83cb7c5,0xb6ebb5d1,0xb8e6b892,0xb880b7fb,0xb983b936,0xb971b8fc,0xba12b9cc,0xba42b9de,0xba91ba53,0xbaefba9d,0xbafebaca,0xbb74bb37,0xbb5abb2e,0xbbcebba6,
0xbb40bb6c,0xbbb2bbd8,0xbad9bb0f,0xbb43bb80,0xba5dba9d,0xbaa6bafa,0xb9cfba18,0xb9e0ba48,0xb92fb981,0xb8f5b96e,0xb880b8d9,0xb7d5b873,0xb788b824,0xb590b6b8,0xb5fab6c3,0xb251b460,
0x367935a2,0x34113197,0x380b374b,0x3684354f,0x38cd386e,0x386637af,0x397e3928,0x396c38ed,0x3a1e39d1,0x3a4e39e2,0x3aa93a66,0x3b043aaf,0x3b1f3ae7,0x3b8c3b4e,0x3b7d3b51,0x3be03bbd,
0x3b613b8d,0x3bc73be8,0x3af53b2e,0x3b5a3b97,0x3a703ab6,0x3ab73b0f,0x39d33a24,0x39e43a53,0x3921397c,0x38e6396a,0x385c38c0,0x37883859,0x370d37e6,0x350e3651,0x3549362e,0x30de3383,
0xb5e2b4f0,0xb2e4b023,0xb7b4b6cf,0xb61db4cc,0xb8b4b849,0xb84cb761,0xb97ab919,0xb967b8de,0xba2ab9d5,0xba59b9e6,0xbac1ba79,0xbb19bac0,0xbb3dbb03,0xbba2bb65,0xbb9cbb70,0xbbefbbd0,
0xbb7fbbaa,0xbbd8bbf4,0xbb10bb4c,0xbb6fbbac,0xba82bacd,0xbac8bb23,0xb9d7ba30,0xb9e8ba5f,0xb912b978,0xb8d7b965,0xb836b8a7,0xb73ab83e,0xb690b783,0xb48ab5e8,0xb496b596,0xaecfb244,
0x3549343b,0x31a42d58,0x37503651,0x35b33447,0x389a3824,0x38313713,0x3975390b,0x396338cf,0x3a3639d9,0x3a6539ea,0x3ad93a8b,0x3b2d3ad0,0x3b5a3b1d,0x3bb53b7a,0x3bb73b8d,0x3bf93be0,
0x3b9a3bc3,0x3be73bfc,0x3b2a3b67,0x3b833bbe,0x3a943ae4,0x3ad93b37,0x39db3a3c,0x39ec3a6a,0x39033973,0x38c83961,0x3811388d,0x36eb3824,0x3611371e,0x3405357e,0x33c034fc,0x2bc03103,
0xb061a8cf,0x25b230ac,0xb549b383,0xb32eae84,0xb816b6c3,0xb750b57e,0xb95eb8c0,0xb94bb883,0xba70b9ef,0xba9bb9ff,0xbb40bae1,0xbb83bb1d,0xbbc7bb8d,0xbbf5bbcc,0xbbffbbed,0xbbeabbff,
0xbbf2bc00,0xbbfebbe3,0xbb96bbcf,0xbbd2bbf9,0xbae9bb49,0xbb25bb8b,0xb9f1ba75,0xba01baa1,0xb8b9b95c,0xb87bb949,0xb69bb809,0xb555b734,0xb2fdb514,0xad71b2bf,0xa376af7e,0x31662966,
0x2e39a052,0xabf2b21f,0x34de3276,0x32512c5e,0x37f63673,0x3718352c,0x395a38b1,0x39473873,0x3a7b39f3,0x3aa63a03,0x3b523af0,0x3b923b2c,0x3bd63b9f,0x3bfb3bd8,0x3c003bf6,0x3bda3bfc,
0x3bfa3bff,0x3bf93bd1,0x3ba73bdd,0x3bdd3bfd,0x3af83b5b,0x3b333b99,0x39f53a80,0x3a053aab,0x38a93957,0x386b3944,0x364b37db,0x350236fc,0x31ee34a8,0x2a9331e2,0xa8062cf4,0xb2d8ad3f,
0xab5c2af8,0x2e843390,0xb472b166,0xb172a86b,0xb7bfb622,0xb6e0b4d8,0xb955b8a2,0xb942b863,0xba86b9f7,0xbab0ba08,0xbb64bb00,0xbba0bb39,0xbbe3bbaf,0xbbffbbe2,0xbbfdbbfd,0xbbc6bbf5,
0xbbffbbfa,0xbbf1bbba,0xbbb7bbe8,0xbbe7bc00,0xbb07bb6c,0xbb40bba6,0xb9f9ba8b,0xba0abab6,0xb89ab953,0xb85cb940,0xb5fab7a4,0xb4aeb6c3,0xb0deb43b,0xa484b103,0x2cf4a8cf,0x34232fc9,
0x2484ae6b,0xb086b47e,0x34053055,0x30931248,0x378835d1,0x36a73484,0x39503892,0x393d3854,0x3a9139fb,0x3abb3a0c,0x3b743b0f,0x3bad3b47,0x3bed3bbe,0x3c003beb,0x3bf63c00,0x3bae3beb,
0x3c003bf0,0x3be53ba0,0x3bc53bf2,0x3bef3c00,0x3b163b7c,0x3b4d3bb3,0x39fd3a96,0x3a0e3ac0,0x388b394e,0x384c393b,0x35a8376c,0x345a368a,0x2f97339c,0xa4203023,0xafe298b6,0xb4d8b128,
0x31c93531,0x355b37e0,0xaf652839,0x9d7f315a,0xb66db42f,0xb584b1b0,0xb939b844,0xb925b803,0xbac5ba10,0xbaecba20,0xbbb9bb53,0xbbdfbb82,0xbbffbbf2,0xbbe3bc00,0xbb91bbde,0xbaf7bb8a,
0xbbd6bb81,0xbb7cbadf,0xbbf5bbfd,0xbc00bbdd,0xbb5abbbe,0xbb88bbe3,0xba12baca,0xba22baf0,0xb83cb936,0xb7f6b923,0xb405b651,0xb15ab567,0x2a61ae84,0x31e22052,0x358a3269,0x381935a8,
0xb309b5e2,0xb5f4b841,0x2da3ac44,0xa5b2b269,0x363433b4,0x35493103,0x39343834,0x392137e6,0x3acf3a14,0x3af53a24,0x3bc43b60,0x3be73b8d,0x3bfb3bf8,0x3bd63bff,0x3b703bce,0x3ac63b6d,
0x3bc53b5f,0x3b5d3aad,0x3bfa3bf9,0x3bff3bcf,0x3b663bc9,0x3b923bea,0x3a163ad4,0x3a263afa,0x382c3931,0x37d5391e,0x335f3617,0x30ac352c,0xad582cc2,0xb2f0a89d,0xb63ab3a8,0xb869b63f,
0x34233690,0x368a3890,0xabc02e6b,0x2a613377,0xb5fab309,0xb50eb055,0xb92fb824,0xb91cb7c5,0xbad9ba18,0xbafeba28,0xbbcebb6c,0xbbedbb97,0xbbf6bbfc,0xbbc7bbfd,0xbb4cbbba,0xba93bb4d,
0xbbafbb38,0xbb3cba77,0xbbfebbf2,0xbbfcbbbf,0xbb72bbd3,0xbb9cbbf0,0xba1abadd,0xba2abb03,0xb81cb92d,0xb7b4b919,0xb2b3b5dc,0xaffbb4f0,0x2f7ea9fd,0x33fd2c12,0x36e53472,0x38b636d4,
0xb4c0b73a,0xb71eb8dc,0x2839b048,0xacf4b441,0x35bf325d,0x34d22f4c,0x392a3813,0x391737a4,0x3ae23a1c,0x3b073a2c,0x3bd73b77,0x3bf33ba1,0x3bee3bff,0x3bb63bfa,0x3b233ba4,0x3a5b3b2a,
0x3b973b0d,0x3b183a3e,0x3c003be9,0x3bf73bad,0x3b7d3bdb,0x3ba63bf5,0x3a1e3ae7,0x3a2e3b0c,0x380b3928,0x37933914,0x320735a2,0x2e9d34b4,0xb0d124e9,0xb484add5,0xb78eb50e,0xb901b767,
0xb97239ba,0x39dc3996,0xb8323ab5,0x3ad0385d,0x3927b9fe,0xba1fb94d,0x37b7bae9,0xbb02b807,0xb8d83a3f,0x3a5e3900,0xb7053b1a,0x3b30375e,0x3887ba7c,0xba99b8b0,0x364ebb46,0xbb5ab6aa,
0xb90039dc,0x3a3f3972,0xad7e3be6,0x3bf83115,0x3807ba99,0xbae9b887,0xabd9bc00,0xbbfca248,0xb5f13b30,0x3b6e3705,0x32a13bed,0x3bd4b04e,0x3365bba0,0xbbc9b4d5,0xb593bbaf,0xbb803475,
0xb88739fe,0x3a99394d,0x35f13bbc,0x3b6eb414,0x3593bb1a,0xbb80b75e,0xb8b0bb02,0xba7c37b7,0xaf0e3bc9,0x3bf43365,0x3a1f39dc,0x3927b972,0xb04ebc00,0xbbed2248,0xbb30b85d,0xb7053ab5,
0xb8073a1f,0x3ae93927,0x39fe3a3f,0x394db900,0x31dbbb80,0xbbddb593,0xbb6eb832,0xb5f13ad0,0x31153c00,0x3be62248,0x3bff32a1,0x28b6bbd4,0xb7b7bb91,0xbb023534,0xbba0304e,0x34d53bed,
0xb7053a3f,0x3b303900,0x3bbc375e,0x3414bb1a,0x2248bbc9,0xbc00b365,0xbbdda8b6,0x31db3bff,0x36aa3bd4,0x3b46b2a1,0x3a7cb64e,0xb8b0bb5a,0xba1fba5e,0xb92738d8,0xb7b739fe,0x3b02394d,
0xb5f13a5e,0x3b6e38d8,0x3bd42bd9,0xb2a1bbfc,0xb115bbf4,0xbbe6af0e,0xb9dc375e,0x39723b1a,0x39273b46,0x3a1fb6aa,0x3475bad0,0xbbafb832,0xbb91b887,0xb5343a99,0x34143c00,0x3bbc2248,
0xb4d53a7c,0x3ba038b0,0x3a3fb593,0xb900bb80,0xb534bc00,0xbb912248,0xb4143ab5,0x3bbc385d,0x3a993a5e,0x3887b8d8,0xb5f1bbfc,0xbb6e2bd9,0xbbffb475,0x28b63baf,0x3ad03a1f,0x3832b927,
0xb3653a99,0x3bc93887,0x36aab996,0xbb46b9ba,0xb7b7bbed,0xbb02304e,0x34d53bfc,0x3ba02bd9,0x3b913927,0x3534ba1f,0xbae9ba3f,0xb8073900,0xbb5a28b6,0x364e3bff,0x3bd43115,0xb2a1bbe6,
0xb1153ab5,0x3be6385d,0xa8b6bb6e,0xbbffb5f1,0xb900bbbc,0xba3f3414,0x3a1f3b30,0x3927b705,0x3bfc375e,0x2bd9bb1a,0xbbedb475,0x304e3baf,0xb9ba3593,0x39963b80,0x3887b832,0xba99bad0,
0xad7e3ad0,0x3bf83832,0xb7b7bbff,0xbb0228b6,0xb9febb6e,0xb94d35f1,0x3bed3887,0x304eba99,0x3bd43414,0xb2a1bbbc,0xb9963534,0x39ba3b91,0xb6aa3900,0x3b463a3f,0xb115bba0,0xbbe6b4d5,
0xa2483ae9,0x3c003807,0xba99bb30,0xb8873705,0xbad0bb02,0xb83237b7,0x3b462d7e,0xb6aabbf8,0x3b1a28b6,0xb75ebbff,0xaf0e3a7c,0x3bf438b0,0xabd93ab5,0x3bfc385d,0xba5ebb5a,0xb8d8364e,
0x2bd93b02,0x3bfc37b7,0xbbedb927,0xb04e3a1f,0xbb6eba7c,0xb5f138b0,0x385db6aa,0xbab5bb46,0x39dcb1db,0xb972bbdd,0x38323c00,0x3ad02248,0x34d53bbc,0x3ba03414,0xbbf4b705,0x2f0e3b30,
0x304e3b1a,0x3bed375e,0xbb91b475,0x35343baf,0xbbd4b9dc,0xb2a13972,0x2248ba7c,0xbc00b8b0,0x3832b64e,0xbad0bb5a,0x3b803a99,0x3593b887,0x39003bfc,0x3a3fabd9,0xb9273414,0x3a1f3bbc,
0x32a13b30,0x3bd43705,0xb996304e,0x39ba3bed,0xbbffb927,0xa8b63a1f,0xb832bbf4,0xbad0af0e,0x3475b8b0,0xbbafba7c,0x3ba03593,0xb4d5bb80,0x3ae93b6e,0x3807b5f1,0x2bd93a99,0x3bfc3887,
0x34753b46,0x3baf36aa,0xb4d53832,0x3ba03ad0,0xbbedb85d,0x304e3ab5,0xbb30bb5a,0xb705364e,0x2248b9fe,0xbc00b94d,0x3887b414,0xba99bbbc,0x3be63a1f,0x3115b927,0x39dc3bf4,0x3972af0e,
0x35933b5a,0x3b80364e,0x31153a99,0x3be63887,0xbba0b705,0x34d53b30,0xbbf4b8d8,0x2f0e3a5e,0xb414bb02,0xbbbcb7b7,0xabd9ba1f,0xbbfcb927,0x3bd43832,0xb2a1bad0,0x3c003972,0xa248b9dc,
0x36aa3b6e,0x3b4635f1,0x38b03bdd,0x3a7c31db,0xbb1ab534,0x375e3b91,0xba3fb04e,0x39003bed,0xb807bbaf,0xbae9b475,0xb94dbbf8,0xb9fead7e,0x3ab53365,0xb85dbbc9,0x39ba28b6,0xb996bbff,
0x37b73b80,0x3b023593,0x3b1a3bc9,0x375eb365,0xba5eb2a1,0x38d83bd4,0xb53435f1,0x3b913b6e,0xb9babbfc,0xb996abd9,0xbbddbae9,0xb1db3807,0x38b0ad7e,0xba7cbbf8,0x28b6b900,0xbbffba3f,
0x385d3b91,0x3ab53534,0x3c003a5e,0x2248b8d8,0xb972ad7e,0x39dc3bf8,0x33653a3f,0x3bc93900,0xbb02bbe6,0xb7b73115,0xbb1ab6aa,0x375e3b46,0x3414b64e,0xbbbcbb5a,0xb94dbbdd,0xb9feb1db,
0x38d83ba0,0x3a5e34d5,0x3b3037b7,0xb705bb02,0xb85d28b6,0x3ab53bff,0x39ba3be6,0x39963115,0xbbc9bb6e,0xb36535f1,0xb6aa31db,0x3b463bdd,0xaf0eb94d,0xbbf4b9fe,0xbbf8bae9,0xad7e3807,
0x394d3baf,0x39fe3475,0x38d82d7e,0xba5ebbf8,0xb64e3115,0x3b5a3be6,0x3bd43b80,0x32a1b593,0xbbffba99,0x28b63887,0x336539ba,0x3bc93996,0xb75ebae9,0xbb1ab807,0xba3fb534,0x39003b91,
0x39ba3bbc,0x39963414,0x31dbb534,0xbbddbb91,0xb3653475,0x3bc93baf,0x3b803927,0xb593ba1f,0xbba0b972,0x34d539dc,0x3a3f3be6,0x39003115,0xb9febbd4,0xb94db2a1,0xb04e35f1,0x3bed3b6e,
0x3a1f3bc9,0x39273365,0xb475b972,0xbbafb9dc,0xabd9364e,0x3bfc3b5a,0x38d831db,0xba5ebbdd,0xbab5b807,0x385d3ae9,0x3c003b30,0x2248b705,0xbb80bbf4,0xb5932f0e,0x38b03b1a,0x3a7c375e,
0x3a7c3bd4,0x38b032a1,0xb972bb5a,0xb9dcb64e,0x2f0e3807,0x3bf43ae9,0x2d7eb534,0xbbf8bb91,0xb94db4d5,0x39fe3ba0,0x3a5e37b7,0xb8d8bb02,0xbc00bb46,0x224836aa,0x3bdd3bc9,0x31dbb365,
0x3ad03bdd,0x383231db,0xbb80bc00,0xb5932248,0x347538d8,0x3baf3a5e,0xb75eb9fe,0xbb1ab94d,0xb705ad7e,0x3b303bf8,0x3414af0e,0xbbbcbbf4,0xbb6eb9dc,0x35f13972,0x3ab538b0,0xb85dba7c,
0x3b1a3be6,0x375e3115,0xbbf4bb46,0x2f0e36aa,0x37053996,0x3b3039ba,0xbae9bbd4,0xb807b2a1,0xb1db304e,0x3bdd3bed,0xb64eb94d,0xbb5ab9fe,0xb9dcb7b7,0x39723b02,0x3365ad7e,0xbbc9bbf8,
0x3b5a3bed,0x364e304e,0xbab5b94d,0x385d39fe,0x38b03a3f,0x3a7c3900,0xbbffbba0,0x28b634d5,0x2d7e3593,0x3bf83b80,0xbb02bbc9,0xb7b7b365,0xb705b1db,0x3b303bdd,0xb807b9ba,0xbae9b996,
0x3b913bf4,0x35342f0e,0xb807b4d5,0x3ae93ba0,0x39ba3ad0,0x39963832,0xba99b972,0x388739dc,0x3593385d,0x3b803ab5,0xbbe6bb6e,0x311535f1,0xad7e304e,0x3bf83bed,0xbbafbbfc,0xb475abd9,
0x3bbc3bf8,0x34142d7e,0xabd92f0e,0x3bfc3bf4,0x3a993b46,0x388736aa,0xb64eb365,0x3b5a3bc9,0x38b039ba,0x3a7c3996,0xb972b85d,0x39dc3ab5,0x34753705,0x3baf3b30,0xbb1aba5e,0x375e38d8,
0x3bdd3bfc,0x31db2bd9,0x364e3807,0x3b5a3ae9,0x3b463ba0,0x36aa34d5,0x31153475,0x3be63baf,0x3a3f3ad0,0x39003832,0xad7e28b6,0x3bf83bff,0x38d83996,0x3a5e39ba,0xb534b2a1,0x3b913bd4,
0x3bf43bff,0x2f0e28b6,0x3a1f3a7c,0x392738b0,0x3bbc3bdd,0x341431db,0x394d39ba,0x39fe3996,0x3b5a3b91,0x364e3534,0x385d38d8,0x3ab53a5e,0x3ad03b1a,0x3832375e,0x36aa37b7,0x3b463b02,
0x3bff3c00,0x28b62248,0x3bc93bd4,0x336532a1,0x3bf83bfc,0x2d7e2bd9,0x3baf3bbc,0x34753414,0x3bed3bf4,0x304e2f0e,0x3b913ba0,0x353434d5,0x3bdd3be6,0x31db3115,0x3b6e3b80,0x35f13593,
0xb5933b6e,0x3b8035f1,0xb1153bdd,0x3be631db,0x34d5bb91,0xbba0b534,0x2f0ebbed,0xbbf4b04e,0xb4143baf,0x3bbc3475,0xabd93bf8,0x3bfc2d7e,0x32a1bbc9,0xbbd4b365,0x2248bbff,0xbc00a8b6,
0x37b73b46,0x3b02b6aa,0x3b1a3832,0x375ebad0,0xb8d8bab5,0xba5e385d,0xbb91b64e,0xb5343b5a,0x39ba39fe,0x3996b94d,0x3bdd3414,0x31dbbbbc,0xba7cb927,0xb8b03a1f,0xbbffaf0e,0xa8b63bf4,
0x3bd43534,0x32a1bb91,0x39bab8d8,0xb996ba5e,0xbbffad7e,0x28b63bf8,0xb8323a3f,0x3ad03900,0x3bafb115,0xb475bbe6,0x34d5bb46,0xbba0b6aa,0xbae9364e,0x38073b5a,0xabd93bdd,0x3bfc31db,
0x3a5eb75e,0xb8d8bb1a,0xb705bbaf,0xbb303475,0xb85d39dc,0x3ab53972,0x39ba3a7c,0x3996b8b0,0x3365bb5a,0xbbc9b64e,0xbb46b887,0xb6aa3a99,0x2f0e3bfc,0x3bf42bd9,0x3bf83414,0x2d7ebbbc,
0x2bd9bbaf,0xbbfcb475,0xbbedad7e,0x304e3bf8,0x35f13be6,0x3b6eb115,0x3ab5b593,0xb85dbb80,0xb9dcba99,0xb9723887,0xb83239ba,0x3ad03996,0x3ba03807,0x34d5bae9,0x2f0ebb91,0xbbf4b534,
0xb9babae9,0xb9963807,0xb1db3b30,0x3bdd3705,0x3bc937b7,0x3365bb02,0xb593bbf8,0xbb802d7e,0xbba028b6,0x34d53bff,0x3a3f3a7c,0x3900b8b0,0x394db85d,0xb9febab5,0xbbedb64e,0xb04e3b5a,
0xbbf8b365,0x2d7e3bc9,0x3b0239dc,0x37b7b972,0x39feb64e,0xb94dbb5a,0xbbedb1db,0x304e3bdd,0xb2a13ae9,0x3bd43807,0x39bab705,0xb996bb30,0xb6aabbf4,0xbb462f0e,0xb1153b1a,0x3be6375e,
0xb8b0385d,0x3a7c3ab5,0x39dcb5f1,0xb972bb6e,0xaf0ebbbc,0xbbf4b414,0xad7e3b30,0x3bf83705,0x39fe3b1a,0x394db75e,0xb8d8bbaf,0xba5e3475,0xbc00b593,0x22483b80,0x3bdd3832,0x31dbbad0,
0x33653bdd,0x3bc931db,0xb6aabc00,0xbb462248,0xbb02ba5e,0xb7b738d8,0x3ba0394d,0x34d5b9fe,0x3b912d7e,0xb534bbf8,0xbae92f0e,0x38073bf4,0xb64e3972,0x3b5a39dc,0x32a1ba7c,0xbbd4b8b0,
0x3b1a3a7c,0x375eb8b0,0xbbf4b593,0x2f0e3b80,0xbb30a248,0x37053c00,0x3807b85d,0xbae9bab5,0x31dbba5e,0xbbddb8d8,0x364e3bfc,0x3b5a2bd9,0x39723baf,0x39dcb475,0xbbc9b927,0xb3653a1f,
0x3b6e304e,0xb5f1bbed,0xb2a139fe,0x3bd4394d,0xb1153a3f,0x3be63900,0xb9dcbba0,0xb97234d5,0xba1fbb80,0xb9273593,0x3baf3365,0xb475bbc9,0x3b9131db,0xb534bbdd,0xb41439ba,0x3bbc3996,
0x3534b900,0xbb91ba3f,0x3ae93b1a,0x3807b75e,0x39ba3bc9,0x3996b365,0xba9928b6,0x38873bff,0xbb80b2a1,0x35933bd4,0xb115bb5a,0xbbe6b64e,0x2d7eba5e,0xbbf8b8d8,0x3baf39fe,0x3475b94d,
0xb807bbf8,0xbae9ad7e,0x39feaf0e,0xb94dbbf4,0x3bdd36aa,0xb1dbbb46,0x35f13bc9,0x3b6e3365,0xb11539ba,0x3be63996,0xbbffb85d,0x28b63ab5,0xbb02bb30,0xb7b73705,0x34d5b8d8,0xbba0ba5e,
0xbbddb9fe,0xb1db394d,0xb64ebbbc,0xbb5ab414,0x36aab75e,0xbb46bb1a,0x3be637b7,0xb115bb02,0x3a3f3bc9,0x3900b365,0xad7e39dc,0x3bf83972,0xba5ea248,0x38d83c00,0xbb91bab5,0xb534385d,
0xba3fa8b6,0x39003bff,0xbbf8b8b0,0x2d7e3a7c,0xb807bbdd,0xbae9b1db,0x2bd9b9ba,0xbbfcb996,0x3b6e3534,0xb5f1bb91,0x3bd43a5e,0x32a1b8d8,0x33653b1a,0x3bc9375e,0xb59337b7,0x3b803b02,
0xa8b63996,0x3bff39ba,0xb365385d,0x3bc93ab5,0xbbf8b9fe,0xad7e394d,0xbbafbae9,0xb4753807,0x304eb900,0xbbedba3f,0x3534b75e,0xbb91bb1a,0x3bdd3a7c,0x31dbb8b0,0x3b6e3b46,0x35f1b6aa,
0x39dc3c00,0x3972a248,0x3ad03bd4,0x3832b2a1,0xb9272bd9,0x3a1f3bfc,0xb7b73414,0x3b023bbc,0xba5ebbf4,0xb8d82f0e,0xbb30bba0,0xb70534d5,0x3887b115,0xba99bbe6,0x364eb593,0xbb5abb80,
0x3bf43972,0xaf0eb9dc,0x3a1f3115,0xb927bbe6,0x34143a99,0x3bbc3887,0x39fe3c00,0x394d2248,0xbb5ab705,0x364e3b30,0xb85d304e,0x3ab53bed,0xb832bba0,0xbad0b4d5,0xbb46bbaf,0xb6aa3475,
0x3887abd9,0xba99bbfc,0xb5f1bae9,0xbb6eb807,0x3b803ba0,0x3593b4d5,0x3a7c3475,0xb8b0bbaf,0xaf0e3832,0x3bf43ad0,0x3a1f3bff,0x392728b6,0xbbedb996,0x304e39ba,0xb70532a1,0x3b303bd4,
0xb414ba1f,0xbbbcb927,0xbbfcba3f,0x2bd93900,0x3a993593,0xb887bb80,0xb64ebad0,0xbb5ab832,0x3a7c3c00,0x38b02248,0x39dc32a1,0xb972bbd4,0xb4753534,0x3baf3b91,0x3b1a3bed,0x375eb04e,
0xbb30bbf4,0xb7052f0e,0xb41434d5,0x3bbc3ba0,0x2248b832,0xbc00bad0,0xbbddb9dc,0x31db3972,0x3b46385d,0xb6aabab5,0xb8b0bb6e,0xba7cb5f1,0x3a1f3bed,0x3927304e,0x37b7abd9,0xbb02bbfc,
0xbb5ab8d8,0x364e3a5e,0x3ab53bfc,0x385d2bd9,0xba7cbbf4,0xb8b0af0e,0xa8b6375e,0x3bff3b1a,0x2d7eb6aa,0xbbf8bb46,0xbb02b832,0x37b73ad0,0x3b303887,0xb705ba99,0xbae9bc00,0xb807a248,
0xb4d53115,0x3ba03be6,0x3a3f36aa,0xb900bb46,0xbb91b996,0x353439ba,0x3bbc3bd4,0x3414b2a1,0xba99bbed,0xb887b04e,0x35f139fe,0x3b6e394d,0xa8b6b7b7,0xbbffbb02,0xb832ad7e,0x3ad03bf8,
0x38323a99,0x3ad03887,0xb593b996,0xbb80b9ba,0xb475304e,0x3baf3bed,0x375e2bd9,0xbb1abbfc,0xbb30b927,0x37053a1f,0x3bbc3a3f,0xb414b900,0xbb6ebbff,0xb5f128b6,0x3ab53be6,0x385d3115,
0x3be63bd4,0x3115b2a1,0xbbffbb5a,0x28b6364e,0x39003ae9,0x3a3f3807,0xba1fbb91,0xb927b534,0xabd934d5,0x3bfc3ba0,0xb04eb7b7,0xbbedbb02,0xb9bab6aa,0x39963b46,0x38873365,0xba99bbc9,
0x3a1f3832,0xb927bad0,0xb47528b6,0x3baf3bff,0x3bfc3b6e,0xabd9b5f1,0xba5eb887,0x38d83a99,0x3ab53bbc,0x385d3414,0xbc00bb91,0x22483534,0x35933900,0x3b803a3f,0xba7cbba0,0xb8b0b4d5,
0x2248b414,0xbc00bbbc,0x3a993b91,0x38873534,0x38323475,0xbad0bbaf,0x36aa3927,0x3b463a1f,0x3b1a39dc,0xb75eb972,0xaf0e3115,0x3bf43be6,0x3bfc3bd4,0x2bd9b2a1,0xb8d8b5f1,0x3a5e3b6e,
0xb9febb02,0xb94db7b7,0x3a5e3927,0xb8d8ba1f,0xb64eb8b0,0xbb5aba7c,0x3bd43b46,0xb2a1b6aa,0x28b6b1db,0xbbffbbdd,0x3bc93c00,0x33652248,0x375e3414,0xbb1abbbc,0x3a3f3b30,0x39003705,
0xbbedbba0,0x304e34d5,0xb534b7b7,0xbb91bb02,0xbbd4bbff,0xb2a1a8b6,0x2248b115,0xbc00bbe6,0xbad0bb6e,0xb832b5f1,0x359331db,0xbb80bbdd,0xb900b9fe,0xba3fb94d,0x39273807,0xba1fbae9,
0xb85db705,0x3ab53b30,0xbc00bbed,0x2248304e,0xb9dcb927,0x39723a1f,0xbbc9bbf4,0xb365af0e,0xbb02ba7c,0x37b738b0,0xbb1abb80,0xb75eb593,0xbbbcbb6e,0x341435f1,0xb9feba99,0xb94db887,
0x34753593,0x3baf3b80,0xb4d5b365,0x3ba03bc9,0x304e32a1,0x3bed3bd4,0xb705b5f1,0x3b303b6e,0xa2482bd9,0x3c003bfc,0xb887b807,0x3a993ae9,0xb115ad7e,0x3be63bf8,0xb972b900,0x39dc3a3f,
0x3b463b5a,0x36aa364e,0x3a7c3a99,0x38b03887,0x3b1a3b30,0x375e3705,0x3a3f3a5e,0x390038d8,0x3ae93b02,0x380737b7,0x39fe3a1f,0x394d3927,0x3ab53ad0,0x385d3832,0x39ba39dc,0x39963972,
0x28b63c00,0x3bffa248,0x33653bd4,0x3bc9b2a1,0xad7ebbfc,0xbbf82bd9,0xb475bbbc,0xbbaf3414,0x304e3bf4,0x3bedaf0e,0x35343ba0,0x3b91b4d5,0xb1dbbbe6,0xbbdd3115,0xb5f1bb80,0xbb6e3593,
0x3bf4a8b6,0xaf0ebbff,0x3a1fb8b0,0xb927ba7c,0xbbbc31db,0x34143bdd,0xb94d3996,0x39fe39ba,0x3b5ab534,0xb64ebb91,0x385dba5e,0xbab5b8d8,0xbad0375e,0x38323b1a,0xb6aa3b02,0x3b4637b7,
0xb1dbbbfc,0xbbdd2bd9,0xbb5ab807,0xb64e3ae9,0x36aa3ba0,0x3b46b4d5,0x3be63475,0x3115bbaf,0xb900bad0,0xba3f3832,0xbbf8a8b6,0x2d7e3bff,0x3a5e3996,0x38d8b9ba,0x3b91b2a1,0xb534bbd4,
0xbbbc2d7e,0x34143bf8,0x2bd93bf4,0x3bfc2f0e,0x3a99b6aa,0xb887bb46,0xb64ebbc9,0xbb5a3365,0xb8b03996,0x3a7c39ba,0x39723ab5,0x39dcb85d,0x3475bb30,0xbbafb705,0xbb1ab8d8,0xb75e3a5e,
0x35343bf4,0x3b91af0e,0x3ae9b4d5,0xb807bba0,0xb996bad0,0xb9ba3832,0xb8873972,0x3a9939dc,0x3b80385d,0x3593bab5,0x3115bb6e,0xbbe6b5f1,0xbbf8b04e,0x2d7e3bed,0x34753bfc,0x3bafabd9,
0x3b5ab04e,0xb64ebbed,0xbab5b9fe,0xb85d394d,0xb8b03900,0x3a7c3a3f,0x3bff34d5,0x28b6bba0,0x2d7ebb80,0xbbf8b593,0xbb023365,0x37b73bc9,0x37053bdd,0x3b30b1db,0x3807b996,0xbae9b9ba,
0xb75ebbe6,0xbb1a3115,0xaf0e3b46,0x3bf436aa,0x3b303996,0x3705b9ba,0xb807bbd4,0xbae932a1,0xbbddb04e,0x31db3bed,0x3b5a394d,0x364eb9fe,0x3972b7b7,0xb9dcbb02,0xbbc9ad7e,0x33653bf8,
0xbad031db,0x38323bdd,0x3b802248,0xb593bc00,0x3475ba5e,0xbbafb8d8,0xb75e394d,0x3b1a39fe,0x37053bf8,0x3b30ad7e,0xb414bbf4,0xbbbcaf0e,0xbb6eb972,0xb5f139dc,0x3ab53a7c,0x385db8b0,
0x38b03bd4,0x3a7cb2a1,0xb9dcbb5a,0xb972364e,0xbbf4b807,0xaf0e3ae9,0x3bf83534,0xad7ebb91,0x39feb4d5,0xb94dbba0,0xb8d837b7,0x3a5e3b02,0xa2483b46,0x3c0036aa,0xb1dbbbc9,0xbbddb365,
0x3a1fb365,0xb927bbc9,0xb47539dc,0x3baf3972,0x2bd93b5a,0x3bfc364e,0xb8d8bbdd,0xba5e31db,0xbab5bae9,0xb85d3807,0x3c003705,0xa248bb30,0x3b802f0e,0xb593bbf4,0xb8b0375e,0x3a7c3b1a,
0xb996bbbc,0xb9ba3414,0x3bdd3534,0xb1dbbb91,0x3bc93475,0xb365bbaf,0xb5933927,0x3b803a1f,0xb4d53972,0x3ba039dc,0xb900bbe6,0xba3f3115,0xb94dbbd4,0xb9fe32a1,0x3bed35f1,0xb04ebb6e,
0xb94d3475,0x39fe3baf,0xb8d8bbf8,0xba5e2d7e,0xb64ebbe6,0xbb5ab115,0x3bd43593,0xb2a1bb80,0x3bff3887,0x28b6ba99,0xb3653996,0x3bc939ba,0xb75e3807,0x3b1a3ae9,0xba3fbb91,0xb9003534,
0x3a5e3ba0,0x38d8b4d5,0xb70537b7,0x3b303b02,0xbab5a8b6,0x385d3bff,0xb996bbe6,0xb9ba3115,0xb365bb6e,0xbbc9b5f1,0x3b4631db,0xb6aabbdd,0x3bf4394d,0x2f0eb9fe,0x2d7e3ae9,0x3bf83807,
0x385db534,0xbab5bb91,0x3c0038d8,0xa248ba5e,0x39723bf8,0x39dcad7e,0xb3653900,0x3bc93a3f,0xbb02b115,0x37b73be6,0xbb1abb46,0xb75e36aa,0xb414bb5a,0xbbbcb64e,0x394db1db,0xb9febbdd,
0xbb02bb80,0xb7b73593,0xb75ebbc9,0xbb1ab365,0x38d8b2a1,0xba5ebbd4,0x3b9135f1,0xb534bb6e,0x39963bfc,0x39baabd9,0x31db3ae9,0x3bdd3807,0xba7cad7e,0x38b03bf8,0xbbffb900,0x28b63a3f,
0xb6aa35f1,0x3b463b6e,0xb8b031db,0x3a7c3bdd,0xbb1abb91,0xb75e3534,0xba3fbbed,0xb900304e,0x3807b475,0xbae9bbaf,0x394dad7e,0xb9febbf8,0x3ab53bc9,0x385db365,0x39ba3bff,0x3996a8b6,
0x3b803b5a,0x3593b64e,0x3be63a99,0x3115b887,0xb4d53705,0x3ba03b30,0xaf0e38d8,0x3bf43a5e,0xbbbcbb02,0xb41437b7,0xbbfcba1f,0xabd93927,0x32a1b832,0xbbd4bad0,0x2248b972,0xbc00b9dc,
0x3475b6aa,0xbbafbb46,0xb4d5bad0,0xbba0b832,0x3bed3ab5,0x304eb85d,0x3b30364e,0xb705bb5a,0x2248394d,0x3c0039fe,0x38873bbc,0x3a993414,0xbbe6b927,0x31153a1f,0xb9dcaf0e,0x39723bf4,
0xbbd4bb30,0xb2a13705,0xb9bab04e,0x39963bed,0xa8b6b927,0xbbffba1f,0xbad0bbf4,0xb8322f0e,0x3baf38b0,0xb475ba7c,0x34d5b593,0xbba0bb80,0x38073b6e,0x3ae935f1,0x3bfc3a99,0x2bd9b887,
0xb04e375e,0x3bed3b1a,0x3b913baf,0x3534b475,0xbbd4b972,0x32a139dc,0x224838b0,0x3c003a7c,0xb832bb5a,0xbad0b64e,0xbb80b887,0x35933a99,0x39002bd9,0xba3fbbfc,0xb927bbbc,0xba1fb414,
0x3bfc3b02,0x2bd9b7b7,0xb04eb927,0xbbedba1f,0x35f13a7c,0x3b6e38b0,0x3ab536aa,0xb85dbb46,0xb972b1db,0x39dc3bdd,0x3ad03c00,0x3832a248,0xbba0bbbc,0xb4d53414,0xaf0e3705,0x3bf43b30,
0xa248b807,0xbc00bae9,0xba99b705,0x38873b30,0x3ad037b7,0xb832bb02,0xbb46bbf8,0xb6aa2d7e,0x3b1a3bff,0x375ea8b6,0xaf0eb8b0,0xbbf4ba7c,0x2bd9385d,0x3bfc3ab5,0x3a5e364e,0xb8d8bb5a,
0xbbf8bad0,0x2d7e3832,0x3b023bff,0x37b728b6,0xb94dbb6e,0xb9feb5f1,0x304e3887,0x3bed3a99,0x32a1b414,0xbbd4bbbc,0xb9bab534,0x39963b91,0x3b463900,0xb6aaba3f,0xbbe6bba0,0xb11534d5,
0x3115385d,0x3be63ab5,0x28b6b5f1,0xbbffbb6e,0xb900b414,0x3a3f3bbc,0x3a1f3705,0xb927bb30,0xbbfcbb1a,0x2bd9375e,0x3bed3baf,0x304eb475,0xb9babb80,0xb996b593,0x38873ad0,0x3a993832,
0x3bc93a99,0xb365b887,0xbb46b996,0x36aa39ba,0x3b023bed,0x37b7304e,0xbba0bbfc,0xb4d52bd9,0x35343927,0x3b913a1f,0xb807ba3f,0xbae9b900,0xb64ea8b6,0x3b5a3bff,0x32a1b115,0xbbd4bbe6,
0xb4d5b8b0,0xbba0ba7c,0x3a3f3b80,0x39003593,0x35342248,0xbb91bc00,0x3414385d,0x3bbc3ab5,0x3a9938d8,0xb887ba5e,0xb5f1abd9,0x3b6e3bfc,0x3bff3baf,0x28b6b475,0xbad0b927,0x38323a1f,
0xbb6eba5e,0x35f138d8,0x32a1abd9,0xbbd4bbfc,0xbbe6bbf4,0xb1152f0e,0x3972375e,0xb9dcbb1a,0xba1fbb46,0xb927b6aa,0x3baf3ad0,0xb475b832,0xb534b887,0xbb91ba99,0x3bbc3c00,0x3414a248,
0x37053900,0x3b303a3f,0xbbbcbb1a,0x3414375e,0x22483365,0x3c003bc9,0xbbddbbff,0xb1db28b6,0xb6aab2a1,0x3b463bd4,0xba7cbb5a,0xb8b0b64e,0xba1fb8d8,0x39273a5e,0xb7b7b94d,0xbb02b9fe,
0x3ae93a1f,0xb807b927,0x394d3a3f,0x39fe3900,0x3bdd3b80,0xb1dbb593,0x35f13832,0x3b6e3ad0,0x3be63c00,0x3115a248,0x28b632a1,0x3bff3bd4,0x3b023b91,0x37b73534,0xb4d5b04e,0x3ba03bed,
0xb887b94d,0xba99b9fe,0x35f13414,0xbb6ebbbc,0xb593b75e,0xbb80bb1a,0x38b037b7,0xba7cbb02,0xaf0eb365,0xbbf4bbc9,0x3a1f3972,0xb927b9dc,0x304e2248,0xbbedbc00,0x3b303ab5,0xb705b85d,
0xba3fb9dc,0x39003972,0xbbf8bbe6,0x2d7e3115,0xbae9ba99,0x38073887,0xbbfcbc00,0xabd92248,0xbb6ebb30,0x35f13705,0xbbd4bbed,0xb2a1b04e,0xbbc9bba0,0x336534d5,0xbb80bbaf,0xb593b475,
0x39723996,0x39dc39ba,0x3832385d,0x3ad03ab5,0x3927394d,0x3a1f39fe,0x37b73807,0x3b023ae9,0x38d83900,0x3a5e3a3f,0x3705375e,0x3b303b1a,0x388738b0,0x3a993a7c,0x364e36aa,0x3b5a3b46,
0x36aa3b5a,0x3b46b64e,0x38b03a99,0x3a7cb887,0xb75ebb30,0xbb1a3705,0xb900ba5e,0xba3f38d8,0x38073b02,0x3ae9b7b7,0x394d3a1f,0x39feb927,0xb85dbad0,0xbab53832,0xb996b9dc,0xb9ba3972,
0x3475bb80,0xbbafb593,0xb4d5bbc9,0xbba03365,0xb04e3bd4,0x3bed32a1,0x37053b6e,0x3b30b5f1,0xa248bbfc,0xbc00abd9,0xb887bae9,0xba993807,0x31153bf8,0x3be6ad7e,0x39723a3f,0x39dcb900,
0xbab53705,0x385d3b30,0xa2483bed,0x3c00304e,0x3972b927,0xb9dcba1f,0xb365bbf4,0xbbc92f0e,0xb7b73a7c,0x3b0238b0,0x375e3b80,0x3b1ab593,0x3414bb6e,0xbbbcb5f1,0xb94dba99,0xb9fe3887,
0x3bed34d5,0x304ebba0,0x3534bb02,0xbb91b7b7,0xbbd428b6,0x32a13bff,0x22483be6,0x3c003115,0x3ad0b5f1,0xb832bb6e,0xb593bbdd,0xbb8031db,0xb900394d,0x3a3f39fe,0x39273ae9,0x3a1fb807,
0xb94dbb02,0xb9fe37b7,0xb8d83927,0x3a5e3a1f,0x3b5a38b0,0x364eba7c,0x32a1bb46,0xbbd4b6aa,0xbbffb1db,0x28b63bdd,0x33653c00,0x3bc9a248,0x3b1ab414,0xb75ebbbc,0xb900bb30,0xba3f3705,
0x22483bbc,0x3c003414,0x3a99b534,0xb887bb91,0xb832bbaf,0xbad03475,0xb6aa3a1f,0x3b463927,0x3b1a3972,0x375eb9dc,0xaf0ebbe6,0xbbf4b115,0xbbfcb2a1,0x2bd93bd4,0x38d83b6e,0x3a5eb5f1,
0x3927b832,0xba1fbad0,0xbbafa8b6,0x34753bff,0xabd93b6e,0x3bfc35f1,0x38d8b887,0xba5eba99,0xb85dbbbc,0xbab53414,0xa2483b91,0x3c003534,0x3b803900,0x3593ba3f,0xb8b0bba0,0xba7c34d5,
0xbbe6b2a1,0x31153bd4,0x3bff364e,0x28b6bb5a,0x3900b807,0xba3fbae9,0xba1f3534,0x39273b91,0x2bd93ba0,0x3bfc34d5,0x304ebb02,0xbbedb7b7,0xb9babb46,0xb99636aa,0x38873bc9,0x3a99b365,
0x3ad03a99,0x3832b887,0xbb80b996,0xb59339ba,0xbbafb04e,0x34753bed,0x3b1aabd9,0xb75ebbfc,0x3705b927,0xbb30ba1f,0xb4143a3f,0x3bbc3900,0x35f13bff,0x3b6e28b6,0xb85dbbe6,0xbab53115,
0xb4d5bbe6,0xbba0b115,0x3a3f3b46,0x3900b6aa,0x3b9139ba,0x3534b996,0xbbbcb2a1,0x34143bd4,0xba99304e,0x38873bed,0x35f1b94d,0xbb6eb9fe,0x28b6bb02,0xbbffb7b7,0x38323bf8,0x3ad0ad7e,
0xb64e38d8,0x3b5a3a5e,0xb85dbbfc,0xbab52bd9,0xb8b0bbf4,0xba7c2f0e,0x3bff375e,0xa8b6bb1a,0x3bf836aa,0xad7ebb46,0xb7b73832,0x3b023ad0,0xb7053887,0x3b303a99,0xb807bc00,0xbae92248,
0x3b302f0e,0xb705bbf4,0x34143ba0,0x3bbc34d5,0x22483ad0,0x3c003832,0xbbddb972,0xb1db39dc,0xbb46bab5,0xb6aa385d,0x38b0b5f1,0xba7cbb6e,0x3a1fb04e,0xb927bbed,0x37b73bfc,0x3b022bd9,
0xbbbcba1f,0xb4143927,0x2bd9ba3f,0xbbfcb900,0x3887b593,0xba99bb80,0x3b5a3ad0,0x364eb832,0x38b03c00,0x3a7ca248,0xb97232a1,0x39dc3bd4,0xbbafb534,0x34753b91,0xb75ebbed,0xbb1ab04e,
0x38873bfc,0x3a992bd9,0xb5f13807,0x3b6e3ae9,0xbb80b4d5,0x35933ba0,0xba7cbbaf,0xb8b03475,0xaf0ebad0,0xbbf4b832,0x3a1fa8b6,0xb927bbff,0x3bed39ba,0x304eb996,0x37053bd4,0x3b3032a1,
0x2f0eb972,0xbbf4b9dc,0x3927b115,0xba1fbbe6,0x3bbc3a99,0x3414b887,0x394d3c00,0x39fea248,0xb64e3705,0x3b5a3b30,0xbab5b04e,0x385d3bed,0xbad0bba0,0xb83234d5,0xb6aabbaf,0xbb46b475,
0xb9dca248,0x39723c00,0xbad0b2a1,0x38323bd4,0xb927bbfc,0xba1fabd9,0xb7b7bbbc,0xbb02b414,0x3a5e2f0e,0xb8d8bbf4,0x3b3034d5,0xb705bba0,0x38873be6,0x3a993115,0x364e3b80,0x3b5a3593,
0x3bff3996,0xa8b6b9ba,0x3bc9385d,0xb365bab5,0x2d7e39fe,0x3bf8394d,0x34753ae9,0x3baf3807,0xbbedb900,0x304e3a3f,0xbb91b75e,0x35343b1a,0xb1dbba7c,0xbbddb8b0,0xb5f1bb46,0xbb6eb6aa,
0xba3fbbff,0xb90028b6,0xbbf8ba7c,0xad7e38b0,0x3807b1db,0xbae9bbdd,0xabd9b996,0xbbfcb9ba,0x3b6e3b91,0x35f1b534,0x3bd438d8,0xb2a1ba5e,0xb365375e,0x3bc93b1a,0x35933b02,0x3b8037b7,
0x31db39fe,0x3bdd394d,0x3b5a3bbc,0x364eb414,0xbb46b75e,0x36aa3b1a,0xb11537b7,0x3be63b02,0xb900bbc9,0xba3fb365,0xbbf8b9dc,0x2d7e3972,0x38d8a248,0xba5ebc00,0xb534bab5,0xbb91b85d,
0x3807ad7e,0xbae9bbf8,0xb9febbf4,0xb94daf0e,0x3bdd3b46,0x31dbb6aa,0x35f1b365,0xbb6ebbc9,0x31153996,0x3be639ba,0x3bff3ab5,0x28b6b85d,0xbb02b705,0x37b73b30,0x34d53a5e,0x3ba038d8,
0xbb91b900,0x35343a3f,0x38073b1a,0x3ae9375e,0xb996bbc9,0xb9bab365,0xb887a8b6,0x3a993bff,0x3593b2a1,0xbb80bbd4,0xbbe6bb5a,0xb115364e,0x3bf83a5e,0xad7eb8d8,0xb475b9fe,0xbbafb94d,
0x3b6e3bed,0x35f1b04e,0xb2a1b94d,0xbbd4b9fe,0x31153900,0x3be63a3f,0x39dc34d5,0xb972bba0,0xba1fb593,0x39273b80,0x3baf3bc9,0x3475b365,0xbb91bbdd,0xb53431db,0x34143996,0x3bbc39ba,
0xb75eba7c,0xbb1ab8b0,0xaf0e3593,0x3bf43b80,0x3705a248,0xbb30bc00,0xbae9b85d,0x38073ab5,0x3bdd3a5e,0xb1dbb8d8,0xbb5abbfc,0xb64e2bd9,0x39dc3baf,0x39723475,0xb365b927,0xbbc9ba1f,
0xb36531db,0x3bc93bdd,0x36aa2248,0xbb46bc00,0xbb02b8d8,0x37b73a5e,0x3ba039fe,0xb4d5b94d,0xbb91bbf8,0xb5342d7e,0x3ae93bf4,0x38072f0e,0xb64eb9dc,0xbb5ab972,0x32a138b0,0x3bd43a7c,
0x3a7c385d,0xb8b0bab5,0xb972b5f1,0x39dc3b6e,0x3bf43bbc,0x2f0eb414,0xbbf8bb30,0x2d7e3705,0x394d3b1a,0x39fe375e,0xba5ebbaf,0xb8d8b475,0xa2483593,0x3c003b80,0xb1dbb832,0xbbddbad0,
0xbbf8bbc9,0xad7e3365,0x3b023972,0xb7b7b9dc,0xb9febb5a,0xb94db64e,0x3bed3bdd,0x304eb1db,0xb2a1b807,0xbbd4bae9,0x39ba3b30,0x39963705,0x36aa2f0e,0xbb46bbf4,0x3115375e,0x3be63b1a,
0x39963ae9,0x39ba3807,0xbbddbb30,0x31db3705,0x336537b7,0x3bc93b02,0xbb80bbf8,0xb593ad7e,0xb4d5a8b6,0x3ba03bff,0xb900ba7c,0xba3fb8b0,0xb9feb85d,0x394d3ab5,0xb04eb64e,0xbbedbb5a,
0xabd9b475,0xbbfcbbaf,0x3bed3bf8,0x304ead7e,0x35f13115,0xbb6ebbe6,0x3ab53b80,0x385d3593,0x39dc3887,0xb972ba99,0x38323996,0x3ad039ba,0x3ba03ae9,0xb4d5b807,0x2f0e3534,0x3bf43b91,
0xb8d8b75e,0x3a5e3b1a,0xbb30bbaf,0xb705b475,0xbab5b9dc,0x385d3972,0xb996ba7c,0xb9bab8b0,0xbbc9bb5a,0x3365364e,0xb6aab887,0xbb46ba99,0xbbf4bbfc,0xaf0e2bd9,0xad7eb414,0xbbf8bbbc,
0x3bd43b91,0xb2a1b534,0x39ba3a5e,0x399638d8,0x3bff3bf8,0x28b6ad7e,0x38323900,0x3ad03a3f,0x3baf3be6,0x34753115,0x34d536aa,0x3ba03b46,0x3ae93b5a,0x3807364e,0x2bd931db,0x3bfc3bdd,
0xbb02bb46,0xb7b7b6aa,0xb75eb832,0xbb1abad0,0xba5ebab5,0xb8d8b85d,0xb534b64e,0xbb91bb5a,0xb996b9fe,0xb9bab94d,0xb1dbb414,0xbbddbbbc,0xb8b0b927,0xba7cba1f,0xa8b6af0e,0xbbffbbf4,
0x359335f1,0x3b803b6e,0x311531db,0x3be63bdd,0x34d53534,0x3ba03b91,0x2f0e304e,0x3bf43bed,0x34143475,0x3bbc3baf,0x2bd92d7e,0x3bfc3bf8,0x32a13365,0x3bd43bc9,0x224828b6,0x3c003bff,
0x40000,0x60002,0xc0008,0xe000a,0x380034,0x3a0036,0x40003c,0x42003e,0x6c0068,0x6e006a,0x740070,0x760072,0xa0009c,0xa2009e,0xa800a4,0xaa00a6,
0xd400d0,0xd600d2,0xdc00d8,0xde00da,0x1080104,0x10a0106,0x110010c,0x112010e,0x13c0138,0x13e013a,0x1440140,0x1460142,0x170016c,0x172016e,0x1780174,0x17a0176,
0x1a401a0,0x1a601a2,0x1ac01a8,0x1ae01aa,0x1d801d4,0x1da01d6,0x1e001dc,0x1e201de,0x20c0208,0x20e020a,0x2140210,0x2160212,0x240023c,0x242023e,0x2480244,0x24a0246,
0x2740270,0x2760272,0x27c0278,0x27e027a,0x2a802a4,0x2aa02a6,0x2b002ac,0x2b202ae,0x2dc02d8,0x2de02da,0x2e402e0,0x2e602e2,0x310030c,0x312030e,0x3180314,0x31a0316,
0x3440340,0x3460342,0x34c0348,0x34e034a,0x3780374,0x37a0376,0x380037c,0x382037e,0x3ac03a8,0x3ae03aa,0x3b403b0,0x3b603b2,0x3e003dc,0x3e203de,0x3e803e4,0x3ea03e6,
0x4140410,0x4160412,0x41c0418,0x41e041a,0x4480444,0x44a0446,0x450044c,0x452044e,0x47c0478,0x47e047a,0x4840480,0x4860482,0x4b004ac,0x4b204ae,0x4b804b4,0x4ba04b6,
0x4e404e0,0x4e604e2,0x4ec04e8,0x4ee04ea,0x5180514,0x51a0516,0x520051c,0x522051e,0x54c0548,0x54e054a,0x5540550,0x5560552,0x580057c,0x582057e,0x5880584,0x58a0586,
0x5b405b0,0x5b605b2,0x5bc05b8,0x5be05ba,0x5e805e4,0x5ea05e6,0x5f005ec,0x5f205ee,0x61c0618,0x61e061a,0x6240620,0x6260622,0x650064c,0x652064e,0x6580654,0x65a0656,
0x140010,0x160012,0x120010,0x440012,0x480044,0x4a0046,0x460044,0x780046,0x7c0078,0x7e007a,0x7a0078,0xac007a,0xb000ac,0xb200ae,0xae00ac,0xe000ae,
0xe400e0,0xe600e2,0xe200e0,0x11400e2,0x1180114,0x11a0116,0x1160114,0x1480116,0x14c0148,0x14e014a,0x14a0148,0x17c014a,0x180017c,0x182017e,0x17e017c,0x1b0017e,
0x1b401b0,0x1b601b2,0x1b201b0,0x1e401b2,0x1e801e4,0x1ea01e6,0x1e601e4,0x21801e6,0x21c0218,0x21e021a,0x21a0218,0x24c021a,0x250024c,0x252024e,0x24e024c,0x280024e,
0x2840280,0x2860282,0x2820280,0x2b40282,0x2b802b4,0x2ba02b6,0x2b602b4,0x2e802b6,0x2ec02e8,0x2ee02ea,0x2ea02e8,0x31c02ea,0x320031c,0x322031e,0x31e031c,0x350031e,
0x3540350,0x3560352,0x3520350,0x3840352,0x3880384,0x38a0386,0x3860384,0x3b80386,0x3bc03b8,0x3be03ba,0x3ba03b8,0x3ec03ba,0x3f003ec,0x3f203ee,0x3ee03ec,0x42003ee,
0x4240420,0x4260422,0x4220420,0x4540422,0x4580454,0x45a0456,0x4560454,0x4880456,0x48c0488,0x48e048a,0x48a0488,0x4bc048a,0x4c004bc,0x4c204be,0x4be04bc,0x4f004be,
0x4f404f0,0x4f604f2,0x4f204f0,0x52404f2,0x5280524,0x52a0526,0x5260524,0x5580526,0x55c0558,0x55e055a,0x55a0558,0x58c055a,0x590058c,0x592058e,0x58e058c,0x5c0058e,
0x5c405c0,0x5c605c2,0x5c205c0,0x5f405c2,0x5f805f4,0x5fa05f6,0x5f605f4,0x62805f6,0x62c0628,0x62e062a,0x62a0628,0x65c062a,0x660065c,0x662065e,0x65e065c,0x18065e,
0x180018,0x4c001a,0x1a0018,0x4c001a,0x4c004c,0x80004e,0x4e004c,0x80004e,0x800080,0xb40082,0x820080,0xb40082,0xb400b4,0xe800b6,0xb600b4,0xe800b6,
0xe800e8,0x11c00ea,0xea00e8,0x11c00ea,0x11c011c,0x150011e,0x11e011c,0x150011e,0x1500150,0x1840152,0x1520150,0x1840152,0x1840184,0x1b80186,0x1860184,0x1b80186,
0x1b801b8,0x1ec01ba,0x1ba01b8,0x1ec01ba,0x1ec01ec,0x22001ee,0x1ee01ec,0x22001ee,0x2200220,0x2540222,0x2220220,0x2540222,0x2540254,0x2880256,0x2560254,0x2880256,
0x2880288,0x2bc028a,0x28a0288,0x2bc028a,0x2bc02bc,0x2f002be,0x2be02bc,0x2f002be,0x2f002f0,0x32402f2,0x2f202f0,0x32402f2,0x3240324,0x3580326,0x3260324,0x3580326,
0x3580358,0x38c035a,0x35a0358,0x38c035a,0x38c038c,0x3c0038e,0x38e038c,0x3c0038e,0x3c003c0,0x3f403c2,0x3c203c0,0x3f403c2,0x3f403f4,0x42803f6,0x3f603f4,0x42803f6,
0x4280428,0x45c042a,0x42a0428,0x45c042a,0x45c045c,0x490045e,0x45e045c,0x490045e,0x4900490,0x4c40492,0x4920490,0x4c40492,0x4c404c4,0x4f804c6,0x4c604c4,0x4f804c6,
0x4f804f8,0x52c04fa,0x4fa04f8,0x52c04fa,0x52c052c,0x560052e,0x52e052c,0x560052e,0x5600560,0x5940562,0x5620560,0x5940562,0x5940594,0x5c80596,0x5960594,0x5c80596,
0x5c805c8,0x5fc05ca,0x5ca05c8,0x5fc05ca,0x5fc05fc,0x63005fe,0x5fe05fc,0x63005fe,0x6300630,0x6640632,0x6320630,0x6640632,0x6640664,0x1c0666,0x6660664,0x1c0666,
0x1c001c,0x50001e,0x1e001c,0x50001e,0x500050,0x840052,0x520050,0x840052,0x840084,0xb80086,0x860084,0xb80086,0xb800b8,0xec00ba,0xba00b8,0xec00ba,
0xec00ec,0x12000ee,0xee00ec,0x12000ee,0x1200120,0x1540122,0x1220120,0x1540122,0x1540154,0x1880156,0x1560154,0x1880156,0x1880188,0x1bc018a,0x18a0188,0x1bc018a,
0x1bc01bc,0x1f001be,0x1be01bc,0x1f001be,0x1f001f0,0x22401f2,0x1f201f0,0x22401f2,0x2240224,0x2580226,0x2260224,0x2580226,0x2580258,0x28c025a,0x25a0258,0x28c025a,
0x28c028c,0x2c0028e,0x28e028c,0x2c0028e,0x2c002c0,0x2f402c2,0x2c202c0,0x2f402c2,0x2f402f4,0x32802f6,0x2f602f4,0x32802f6,0x3280328,0x35c032a,0x32a0328,0x35c032a,
0x35c035c,0x390035e,0x35e035c,0x390035e,0x3900390,0x3c40392,0x3920390,0x3c40392,0x3c403c4,0x3f803c6,0x3c603c4,0x3f803c6,0x3f803f8,0x42c03fa,0x3fa03f8,0x42c03fa,
0x42c042c,0x460042e,0x42e042c,0x460042e,0x4600460,0x4940462,0x4620460,0x4940462,0x4940494,0x4c80496,0x4960494,0x4c80496,0x4c804c8,0x4fc04ca,0x4ca04c8,0x4fc04ca,
0x4fc04fc,0x53004fe,0x4fe04fc,0x53004fe,0x5300530,0x5640532,0x5320530,0x5640532,0x5640564,0x5980566,0x5660564,0x5980566,0x5980598,0x5cc059a,0x59a0598,0x5cc059a,
0x5cc05cc,0x60005ce,0x5ce05cc,0x60005ce,0x6000600,0x6340602,0x6020600,0x6340602,0x6340634,0x6680636,0x6360634,0x6680636,0x6680668,0x20066a,0x66a0668,0x20066a,
0x5d605d6,0x60a05d6,0x5d605d6,0x60a060a,0x60a060a,0x63e063e,0x60a060a,0x63e063e,0x63e063e,0x672063e,0x63e063e,0x6720672,0x6720672,0x280028,0x6720672,0x280028,
0x5060506,0x53a0506,0x5060506,0x53a053a,0x53a053a,0x56e056e,0x53a053a,0x56e056e,0x56e056e,0x5a2056e,0x56e056e,0x5a205a2,0x5a205a2,0x5d605d6,0x5a205a2,0x5d605d6,
0x4360436,0x46a0436,0x4360436,0x46a046a,0x46a046a,0x49e049e,0x46a046a,0x49e049e,0x49e049e,0x4d2049e,0x49e049e,0x4d204d2,0x4d204d2,0x5060506,0x4d204d2,0x5060506,
0x3660366,0x39a0366,0x3660366,0x39a039a,0x39a039a,0x3ce03ce,0x39a039a,0x3ce03ce,0x3ce03ce,0x40203ce,0x3ce03ce,0x4020402,0x4020402,0x4360436,0x4020402,0x4360436,
0x2960296,0x2ca0296,0x2960296,0x2ca02ca,0x2ca02ca,0x2fe02fe,0x2ca02ca,0x2fe02fe,0x2fe02fe,0x33202fe,0x2fe02fe,0x3320332,0x3320332,0x3660366,0x3320332,0x3660366,
0x1c601c6,0x1fa01c6,0x1c601c6,0x1fa01fa,0x1fa01fa,0x22e022e,0x1fa01fa,0x22e022e,0x22e022e,0x262022e,0x22e022e,0x2620262,0x2620262,0x2960296,0x2620262,0x2960296,
0xf600f6,0x12a00f6,0xf600f6,0x12a012a,0x12a012a,0x15e015e,0x12a012a,0x15e015e,0x15e015e,0x192015e,0x15e015e,0x1920192,0x1920192,0x1c601c6,0x1920192,0x1c601c6,
0x260026,0x5a0026,0x260026,0x5a005a,0x5a005a,0x8e008e,0x5a005a,0x8e008e,0x8e008e,0xc2008e,0x8e008e,0xc200c2,0xc200c2,0xf600f6,0xc200c2,0xf600f6,
0x5d405d4,0x60805d4,0x5d405d4,0x6080608,0x6080608,0x63c063c,0x6080608,0x63c063c,0x63c063c,0x670063c,0x63c063c,0x6700670,0x6700670,0x260026,0x6700670,0x260026,
0x5040504,0x5380504,0x5040504,0x5380538,0x5380538,0x56c056c,0x5380538,0x56c056c,0x56c056c,0x5a0056c,0x56c056c,0x5a005a0,0x5a005a0,0x5d405d4,0x5a005a0,0x5d405d4,
0x4340434,0x4680434,0x4340434,0x4680468,0x4680468,0x49c049c,0x4680468,0x49c049c,0x49c049c,0x4d0049c,0x49c049c,0x4d004d0,0x4d004d0,0x5040504,0x4d004d0,0x5040504,
0x3640364,0x3980364,0x3640364,0x3980398,0x3980398,0x3cc03cc,0x3980398,0x3cc03cc,0x3cc03cc,0x40003cc,0x3cc03cc,0x4000400,0x4000400,0x4340434,0x4000400,0x4340434,
0x2940294,0x2c80294,0x2940294,0x2c802c8,0x2c802c8,0x2fc02fc,0x2c802c8,0x2fc02fc,0x2fc02fc,0x33002fc,0x2fc02fc,0x3300330,0x3300330,0x3640364,0x3300330,0x3640364,
0x1c401c4,0x1f801c4,0x1c401c4,0x1f801f8,0x1f801f8,0x22c022c,0x1f801f8,0x22c022c,0x22c022c,0x260022c,0x22c022c,0x2600260,0x2600260,0x2940294,0x2600260,0x2940294,
0xf400f4,0x12800f4,0xf400f4,0x1280128,0x1280128,0x15c015c,0x1280128,0x15c015c,0x15c015c,0x190015c,0x15c015c,0x1900190,0x1900190,0x1c401c4,0x1900190,0x1c401c4,
0x240024,0x580024,0x240024,0x580058,0x580058,0x8c008c,0x580058,0x8c008c,0x8c008c,0xc0008c,0x8c008c,0xc000c0,0xc000c0,0xf400f4,0xc000c0,0xf400f4,
0x5d205d2,0x60605d2,0x5d205d2,0x6060606,0x6060606,0x63a063a,0x6060606,0x63a063a,0x63a063a,0x66e063a,0x63a063a,0x66e066e,0x66e066e,0x240024,0x66e066e,0x240024,
0x5020502,0x5360502,0x5020502,0x5360536,0x5360536,0x56a056a,0x5360536,0x56a056a,0x56a056a,0x59e056a,0x56a056a,0x59e059e,0x59e059e,0x5d205d2,0x59e059e,0x5d205d2,
0x4320432,0x4660432,0x4320432,0x4660466,0x4660466,0x49a049a,0x4660466,0x49a049a,0x49a049a,0x4ce049a,0x49a049a,0x4ce04ce,0x4ce04ce,0x5020502,0x4ce04ce,0x5020502,
0x3620362,0x3960362,0x3620362,0x3960396,0x3960396,0x3ca03ca,0x3960396,0x3ca03ca,0x3ca03ca,0x3fe03ca,0x3ca03ca,0x3fe03fe,0x3fe03fe,0x4320432,0x3fe03fe,0x4320432,
0x2920292,0x2c60292,0x2920292,0x2c602c6,0x2c602c6,0x2fa02fa,0x2c602c6,0x2fa02fa,0x2fa02fa,0x32e02fa,0x2fa02fa,0x32e032e,0x32e032e,0x3620362,0x32e032e,0x3620362,
0x1c201c2,0x1f601c2,0x1c201c2,0x1f601f6,0x1f601f6,0x22a022a,0x1f601f6,0x22a022a,0x22a022a,0x25e022a,0x22a022a,0x25e025e,0x25e025e,0x2920292,0x25e025e,0x2920292,
0xf200f2,0x12600f2,0xf200f2,0x1260126,0x1260126,0x15a015a,0x1260126,0x15a015a,0x15a015a,0x18e015a,0x15a015a,0x18e018e,0x18e018e,0x1c201c2,0x18e018e,0x1c201c2,
0x220022,0x560022,0x220022,0x560056,0x560056,0x8a008a,0x560056,0x8a008a,0x8a008a,0xbe008a,0x8a008a,0xbe00be,0xbe00be,0xf200f2,0xbe00be,0xf200f2,
0x5d005d0,0x60405d0,0x5d005d0,0x6040604,0x6040604,0x6380638,0x6040604,0x6380638,0x6380638,0x66c0638,0x6380638,0x66c066c,0x66c066c,0x220022,0x66c066c,0x220022,
0x5000500,0x5340500,0x5000500,0x5340534,0x5340534,0x5680568,0x5340534,0x5680568,0x5680568,0x59c0568,0x5680568,0x59c059c,0x59c059c,0x5d005d0,0x59c059c,0x5d005d0,
0x4300430,0x4640430,0x4300430,0x4640464,0x4640464,0x4980498,0x4640464,0x4980498,0x4980498,0x4cc0498,0x4980498,0x4cc04cc,0x4cc04cc,0x5000500,0x4cc04cc,0x5000500,
0x3600360,0x3940360,0x3600360,0x3940394,0x3940394,0x3c803c8,0x3940394,0x3c803c8,0x3c803c8,0x3fc03c8,0x3c803c8,0x3fc03fc,0x3fc03fc,0x4300430,0x3fc03fc,0x4300430,
0x2900290,0x2c40290,0x2900290,0x2c402c4,0x2c402c4,0x2f802f8,0x2c402c4,0x2f802f8,0x2f802f8,0x32c02f8,0x2f802f8,0x32c032c,0x32c032c,0x3600360,0x32c032c,0x3600360,
0x1c001c0,0x1f401c0,0x1c001c0,0x1f401f4,0x1f401f4,0x2280228,0x1f401f4,0x2280228,0x2280228,0x25c0228,0x2280228,0x25c025c,0x25c025c,0x2900290,0x25c025c,0x2900290,
0xf000f0,0x12400f0,0xf000f0,0x1240124,0x1240124,0x1580158,0x1240124,0x1580158,0x1580158,0x18c0158,0x1580158,0x18c018c,0x18c018c,0x1c001c0,0x18c018c,0x1c001c0,
0x200020,0x540020,0x200020,0x540054,0x540054,0x880088,0x540054,0x880088,0x880088,0xbc0088,0x880088,0xbc00bc,0xbc00bc,0xf000f0,0xbc00bc,0xf000f0,
0x30003000,0x30003000,0x30003000,0x30003000,0x30003000,0x30003000,0x30003000,0x30003000,0x0,0x0,0x0,0x0,0x0,0x0,0x0,0x0,
0x30003000,0x30003000,0x30003000,0x30003000,0x30003000,0x30003000,0x30003000,0x30003000,0x0,0x0,0x0,0x0,0x0,0x0,0x0,0x0,
0x2a1f2da8,0xaf64ada8,0xaa1fada8,0x2f642da8,0x2f643000,0xaa1f0000,0xaf64b000,0x2a1f8000,0x2f642da8,0x2a1f2da8,0xaf64ada8,0xaa1fada8,0x2a1f0000,0x2f643000,0xaa1f0000,0xaf64b000,
0x263e2c72,0xafd9aea7,0xa63eac72,0x2fd92ea7,0x2ea72fd9,0xac72a63e,0xaea7afd9,0x2c72263e,0x2fd92ea7,0x263e2c72,0xafd9aea7,0xa63eac72,0x2c72263e,0x2ea72fd9,0xac72a63e,0xaea7afd9,
0x2da80000,0xada80000,0x2da88000,0xada80000,0x2da83000,0xada8b000,0x2da83000,0xada8b000,0x2da83000,0xada8b000,0x2da83000,0xada8b000,0xada80000,0x2da88000,0xada80000,0x2da88000,
0x2f642a1f,0xaf64aa1f,0x2f642a1f,0xaf64aa1f,0x2a1f2f64,0xaa1faf64,0x2a1f2f64,0xaa1faf64,0x2a1f2f64,0xaa1faf64,0x2a1f2f64,0xaa1faf64,0xaf64aa1f,0x2f642a1f,0xaf64aa1f,0x2f642a1f,
0xaa1f2da8,0x2f642da8,0x2a1fada8,0xaf64ada8,0x2f640000,0xaa1fb000,0xaf640000,0x2a1f3000,0xaf64ada8,0xaa1f2da8,0x2f642da8,0x2a1fada8,0x2a1f3000,0x2f648000,0xaa1fb000,0xaf640000,
0xaea7263e,0x2c722fd9,0x2ea7a63e,0xac72afd9,0x2fd92c72,0x263eaea7,0xafd9ac72,0xa63e2ea7,0xac72afd9,0xaea7263e,0x2c722fd9,0x2ea7a63e,0xa63e2ea7,0x2fd92c72,0x263eaea7,0xafd9ac72,
0xada82da8,0xada82da8,0xada82da8,0xada82da8,0x2da8ada8,0x2da8ada8,0x2da8ada8,0x2da8ada8,0x2da82da8,0x2da82da8,0x2da82da8,0x2da82da8,0xada8ada8,0xada8ada8,0xada8ada8,0xada8ada8,
0x3000,0x3000,0x3000,0x80003000,0x8000b000,0x8000b000,0x8000b000,0x8000b000,0x30000000,0x30008000,0x30008000,0x30008000,0xb0000000,0xb0000000,0xb0000000,0xb0000000,
0x2ea7263e,0xac722fd9,0xaea7a63e,0x2c72afd9,0xafd92c72,0xa63eaea7,0x2fd9ac72,0x263e2ea7,0x2c72afd9,0x2ea7263e,0xac722fd9,0xaea7a63e,0x263e2ea7,0xafd92c72,0xa63eaea7,0x2fd9ac72,
0x2f64ada8,0x2a1f2da8,0xaf642da8,0xaa1fada8,0xaa1f3000,0xaf640000,0x2a1fb000,0x2f648000,0xaa1fada8,0x2f64ada8,0x2a1f2da8,0xaf642da8,0x2f640000,0xaa1f3000,0xaf640000,0x2a1fb000,
0xaa1f2f64,0x2a1faf64,0xaa1f2f64,0x2a1faf64,0x2f64aa1f,0xaf642a1f,0x2f64aa1f,0xaf642a1f,0xaf642a1f,0x2f64aa1f,0xaf642a1f,0x2f64aa1f,0xaa1f2f64,0x2a1faf64,0xaa1f2f64,0x2a1faf64,
0x2da80000,0xada80000,0x2da88000,0xada80000,0x2da8b000,0xada83000,0x2da8b000,0xada83000,0xada83000,0x2da8b000,0xada83000,0x2da8b000,0x2da88000,0xada80000,0x2da88000,0xada88000,
0xa63e2c72,0x2fd9aea7,0x263eac72,0xafd92ea7,0xaea72fd9,0x2c72a63e,0x2ea7afd9,0xac72263e,0xafd92ea7,0xa63e2c72,0x2fd9aea7,0x263eac72,0xac72263e,0xaea72fd9,0x2c72a63e,0x2ea7afd9,
0x2f64ada8,0x2a1fada8,0xaf642da8,0xaa1f2da8,0x2a1f0000,0x2f64b000,0xaa1f0000,0xaf643000,0xaa1f2da8,0x2f64ada8,0x2a1fada8,0xaf642da8,0xaf643000,0x2a1f8000,0x2f64b000,0xaa1f8000,
0xb0003000,0xb0003000,0xb0003000,0xb0003000,0xb0003000,0xb0003000,0xb0003000,0xb0003000,0x0,0x8000,0x8000,0x80008000,0x8000,0x8000,0x8000,0x8000,
0x80000000,0x80000000,0x80008000,0x80008000,0x80000000,0x80008000,0x80008000,0x80008000,0xb0003000,0xb0003000,0xb0003000,0xb0003000,0xb0003000,0xb0003000,0xb0003000,0xb0003000,
0xaa1f2da8,0x2f64ada8,0x2a1fada8,0xaf642da8,0xaf643000,0x2a1f0000,0x2f64b000,0xaa1f8000,0xaf642da8,0xaa1f2da8,0x2f64ada8,0x2a1fada8,0xaa1f0000,0xaf643000,0x2a1f0000,0x2f64b000,
0x2fd9aea7,0x263eac72,0xafd92ea7,0xa63e2c72,0x2c72a63e,0x2ea7afd9,0xac72263e,0xaea72fd9,0xa63e2c72,0x2fd9aea7,0x263eac72,0xafd92ea7,0xaea72fd9,0x2c72a63e,0x2ea7afd9,0xac72263e,
0xada80000,0x2da80000,0xada88000,0x2da80000,0xada83000,0x2da8b000,0xada83000,0x2da8b000,0xada83000,0x2da8b000,0xada83000,0x2da8b000,0x2da80000,0xada88000,0x2da88000,0xada88000,
0xaa1f2f64,0x2a1faf64,0xaa1f2f64,0x2a1faf64,0x2f64aa1f,0xaf642a1f,0x2f64aa1f,0xaf642a1f,0x2f64aa1f,0xaf642a1f,0x2f64aa1f,0xaf642a1f,0x2a1faf64,0xaa1f2f64,0x2a1faf64,0xaa1f2f64,
0x2a1f2da8,0xaf642da8,0xaa1fada8,0x2f64ada8,0xaf640000,0x2a1fb000,0x2f640000,0xaa1f3000,0x2f64ada8,0x2a1f2da8,0xaf642da8,0xaa1fada8,0xaa1f3000,0xaf648000,0x2a1fb000,0x2f640000,
0x2c72afd9,0x2ea7263e,0xac722fd9,0xaea7a63e,0x263e2ea7,0xafd92c72,0xa63eaea7,0x2fd9ac72,0xaea7a63e,0x2c72afd9,0x2ea7263e,0xac722fd9,0x2fd9ac72,0x263e2ea7,0xafd92c72,0xa63eaea7,
0x2da8ada8,0x2da8ada8,0x2da8ada8,0x2da8ada8,0xada82da8,0xada82da8,0xada82da8,0xada82da8,0x2da82da8,0x2da82da8,0x2da82da8,0x2da82da8,0xada8ada8,0xada8ada8,0xada8ada8,0xada8ada8,
0x80003000,0x80003000,0x80003000,0x3000,0xb000,0x8000b000,0xb000,0xb000,0xb0000000,0xb0008000,0xb0008000,0xb0008000,0x30000000,0x30000000,0x30000000,0x30008000,
0x2c722fd9,0x2ea7a63e,0xac72afd9,0xaea7263e,0x263eaea7,0xafd9ac72,0xa63e2ea7,0x2fd92c72,0xaea7263e,0x2c722fd9,0x2ea7a63e,0xac72afd9,0x2fd92c72,0x263eaea7,0xafd9ac72,0xa63e2ea7,
0xaf64ada8,0xaa1f2da8,0x2f642da8,0x2a1fada8,0x2a1f3000,0x2f648000,0xaa1fb000,0xaf648000,0x2a1fada8,0xaf64ada8,0xaa1f2da8,0x2f642da8,0xaf640000,0x2a1f3000,0x2f648000,0xaa1fb000,
0x2f642a1f,0xaf64aa1f,0x2f642a1f,0xaf64aa1f,0x2a1f2f64,0xaa1faf64,0x2a1f2f64,0xaa1faf64,0xaa1faf64,0x2a1f2f64,0xaa1faf64,0x2a1f2f64,0x2f642a1f,0xaf64aa1f,0x2f642a1f,0xaf64aa1f,
0xada80000,0x2da80000,0xada88000,0x2da88000,0xada8b000,0x2da83000,0xada8b000,0x2da83000,0x2da83000,0xada8b000,0x2da83000,0xada8b000,0xada88000,0x2da88000,0xada88000,0x2da80000,
0x2fd92ea7,0x263e2c72,0xafd9aea7,0xa63eac72,0x2c72263e,0x2ea72fd9,0xac72a63e,0xaea7afd9,0xa63eac72,0x2fd92ea7,0x263e2c72,0xafd9aea7,0xaea7afd9,0x2c72263e,0x2ea72fd9,0xac72a63e,
0xaf64ada8,0xaa1fada8,0x2f642da8,0x2a1f2da8,0xaa1f0000,0xaf64b000,0x2a1f0000,0x2f643000,0x2a1f2da8,0xaf64ada8,0xaa1fada8,0x2f642da8,0x2f643000,0xaa1f8000,0xaf64b000,0x2a1f0000,
0x80008000,0x80008000,0x80008000,0x80008000,0x80008000,0x80008000,0x80008000,0x80008000,0x30003000,0x30003000,0x30003000,0x30003000,0x30003000,0x30003000,0x30003000,0x30003000,
0x80008000,0x80008000,0x80008000,0x80008000,0x80008000,0x80008000,0x80008000,0x80008000,0x30003000,0x30003000,0x30003000,0x30003000,0x30003000,0x30003000,0x30003000,0x30003000,
0xaf64ada8,0xaa1fada8,0x2f642da8,0x2a1f2da8,0xaa1f8000,0xaf64b000,0x2a1f8000,0x2f643000,0x2a1f2da8,0xaf64ada8,0xaa1fada8,0x2f642da8,0x2f643000,0xaa1f0000,0xaf64b000,0x2a1f8000,
0xafd9aea7,0xa63eac72,0x2fd92ea7,0x263e2c72,0xac72a63e,0xaea7afd9,0x2c72263e,0x2ea72fd9,0x263e2c72,0xafd9aea7,0xa63eac72,0x2fd92ea7,0x2ea72fd9,0xac72a63e,0xaea7afd9,0x2c72263e,
0x2da83000,0xada8b000,0x2da83000,0xada8b000,0xada80000,0x2da88000,0xada80000,0x2da88000,0xada88000,0x2da88000,0xada80000,0x2da88000,0xada8b000,0x2da83000,0xada8b000,0x2da83000,
0x2a1f2f64,0xaa1faf64,0x2a1f2f64,0xaa1faf64,0xaf64aa1f,0x2f642a1f,0xaf64aa1f,0x2f642a1f,0xaf64aa1f,0x2f642a1f,0xaf64aa1f,0x2f642a1f,0xaa1faf64,0x2a1f2f64,0xaa1faf64,0x2a1f2f64,
0xaf64ada8,0xaa1f2da8,0x2f642da8,0x2a1fada8,0x2a1f3000,0x2f648000,0xaa1fb000,0xaf640000,0x2a1fada8,0xaf64ada8,0xaa1f2da8,0x2f642da8,0xaf648000,0x2a1f3000,0x2f648000,0xaa1fb000,
0xac72afd9,0xaea7263e,0x2c722fd9,0x2ea7a63e,0xa63e2ea7,0x2fd92c72,0x263eaea7,0xafd9ac72,0x2ea7a63e,0xac72afd9,0xaea7263e,0x2c722fd9,0xafd9ac72,0xa63e2ea7,0x2fd92c72,0x263eaea7,
0xada8ada8,0xada8ada8,0xada8ada8,0xada8ada8,0x2da82da8,0x2da82da8,0x2da82da8,0x2da82da8,0xada82da8,0xada82da8,0xada82da8,0xada82da8,0x2da8ada8,0x2da8ada8,0x2da8ada8,0x2da8ada8,
0xb0008000,0xb0000000,0xb0000000,0xb0000000,0x30008000,0x30008000,0x30008000,0x30008000,0x3000,0x3000,0x3000,0x80003000,0x8000b000,0x8000b000,0x8000b000,0x8000b000,
0xac722fd9,0xaea7a63e,0x2c72afd9,0x2ea7263e,0xa63eaea7,0x2fd9ac72,0x263e2ea7,0xafd92c72,0x2ea7263e,0xac722fd9,0xaea7a63e,0x2c72afd9,0xafd92c72,0xa63eaea7,0x2fd9ac72,0x263e2ea7,
0x2a1f2da8,0xaf642da8,0xaa1fada8,0x2f64ada8,0xaf648000,0x2a1fb000,0x2f648000,0xaa1f3000,0x2f64ada8,0x2a1f2da8,0xaf642da8,0xaa1fada8,0xaa1f3000,0xaf640000,0x2a1fb000,0x2f648000,
0xaf642a1f,0x2f64aa1f,0xaf642a1f,0x2f64aa1f,0xaa1f2f64,0x2a1faf64,0xaa1f2f64,0x2a1faf64,0x2a1faf64,0xaa1f2f64,0x2a1faf64,0xaa1f2f64,0xaf642a1f,0x2f64aa1f,0xaf642a1f,0x2f64aa1f,
0xada83000,0x2da8b000,0xada83000,0x2da8b000,0x2da88000,0xada80000,0x2da88000,0xada88000,0xada88000,0x2da88000,0xada80000,0x2da88000,0xada83000,0x2da8b000,0xada83000,0x2da8b000,
0xafd92ea7,0xa63e2c72,0x2fd9aea7,0x263eac72,0xac72263e,0xaea72fd9,0x2c72a63e,0x2ea7afd9,0x263eac72,0xafd92ea7,0xa63e2c72,0x2fd9aea7,0x2ea7afd9,0xac72263e,0xaea72fd9,0x2c72a63e,
0xaa1f2da8,0x2f64ada8,0x2a1fada8,0xaf642da8,0xaf643000,0x2a1f8000,0x2f64b000,0xaa1f8000,0xaf642da8,0xaa1f2da8,0x2f64ada8,0x2a1fada8,0xaa1f8000,0xaf643000,0x2a1f8000,0x2f64b000,
0x80008000,0x80000000,0x80000000,0x0,0x80000000,0x80000000,0x80000000,0x80000000,0xb0003000,0xb0003000,0xb0003000,0xb0003000,0xb0003000,0xb0003000,0xb0003000,0xb0003000,
0x3000b000,0x3000b000,0x3000b000,0x3000b000,0x3000b000,0x3000b000,0x3000b000,0x3000b000,0x80000000,0x80000000,0x80008000,0x80008000,0x80000000,0x80008000,0x80008000,0x80008000,
0x2f64ada8,0x2a1fada8,0xaf642da8,0xaa1f2da8,0x2a1f8000,0x2f64b000,0xaa1f8000,0xaf643000,0xaa1f2da8,0x2f64ada8,0x2a1fada8,0xaf642da8,0xaf643000,0x2a1f0000,0x2f64b000,0xaa1f8000,
0x263eac72,0xafd92ea7,0xa63e2c72,0x2fd9aea7,0x2ea7afd9,0xac72263e,0xaea72fd9,0x2c72a63e,0x2fd9aea7,0x263eac72,0xafd92ea7,0xa63e2c72,0x2c72a63e,0x2ea7afd9,0xac72263e,0xaea72fd9,
0xada83000,0x2da8b000,0xada83000,0x2da8b000,0x2da80000,0xada88000,0x2da88000,0xada88000,0x2da88000,0xada88000,0x2da80000,0xada88000,0x2da8b000,0xada83000,0x2da8b000,0xada83000,
0x2f64aa1f,0xaf642a1f,0x2f64aa1f,0xaf642a1f,0x2a1faf64,0xaa1f2f64,0x2a1faf64,0xaa1f2f64,0x2a1faf64,0xaa1f2f64,0x2a1faf64,0xaa1f2f64,0xaf642a1f,0x2f64aa1f,0xaf642a1f,0x2f64aa1f,
0x2f64ada8,0x2a1f2da8,0xaf642da8,0xaa1fada8,0xaa1f3000,0xaf648000,0x2a1fb000,0x2f640000,0xaa1fada8,0x2f64ada8,0x2a1f2da8,0xaf642da8,0x2f648000,0xaa1f3000,0xaf648000,0x2a1fb000,
0xaea7a63e,0x2c72afd9,0x2ea7263e,0xac722fd9,0x2fd9ac72,0x263e2ea7,0xafd92c72,0xa63eaea7,0xac722fd9,0xaea7a63e,0x2c72afd9,0x2ea7263e,0xa63eaea7,0x2fd9ac72,0x263e2ea7,0xafd92c72,
0xada8ada8,0xada8ada8,0xada8ada8,0xada8ada8,0x2da82da8,0x2da82da8,0x2da82da8,0x2da82da8,0x2da8ada8,0x2da8ada8,0x2da8ada8,0x2da8ada8,0xada82da8,0xada82da8,0xada82da8,0xada82da8,
0x30008000,0x30000000,0x30000000,0x30000000,0xb0008000,0xb0008000,0xb0008000,0xb0000000,0x80003000,0x80003000,0x80003000,0x3000,0xb000,0x8000b000,0xb000,0xb000,
0x2ea7a63e,0xac72afd9,0xaea7263e,0x2c722fd9,0xafd9ac72,0xa63e2ea7,0x2fd92c72,0x263eaea7,0x2c722fd9,0x2ea7a63e,0xac72afd9,0xaea7263e,0x263eaea7,0xafd9ac72,0xa63e2ea7,0x2fd92c72,
0xaa1f2da8,0x2f642da8,0x2a1fada8,0xaf64ada8,0x2f648000,0xaa1fb000,0xaf640000,0x2a1f3000,0xaf64ada8,0xaa1f2da8,0x2f642da8,0x2a1fada8,0x2a1f3000,0x2f648000,0xaa1fb000,0xaf648000,
0xaa1faf64,0x2a1f2f64,0xaa1faf64,0x2a1f2f64,0x2f642a1f,0xaf64aa1f,0x2f642a1f,0xaf64aa1f,0xaf64aa1f,0x2f642a1f,0xaf64aa1f,0x2f642a1f,0xaa1faf64,0x2a1f2f64,0xaa1faf64,0x2a1f2f64,
0x2da83000,0xada8b000,0x2da83000,0xada8b000,0xada88000,0x2da88000,0xada88000,0x2da80000,0x2da88000,0xada88000,0x2da80000,0xada80000,0x2da83000,0xada8b000,0x2da83000,0xada8b000,
0xa63eac72,0x2fd92ea7,0x263e2c72,0xafd9aea7,0xaea7afd9,0x2c72263e,0x2ea72fd9,0xac72a63e,0xafd9aea7,0xa63eac72,0x2fd92ea7,0x263e2c72,0xac72a63e,0xaea7afd9,0x2c72263e,0x2ea72fd9,
0x2a1f2da8,0xaf64ada8,0xaa1fada8,0x2f642da8,0x2f643000,0xaa1f8000,0xaf64b000,0x2a1f0000,0x2f642da8,0x2a1f2da8,0xaf64ada8,0xaa1fada8,0x2a1f8000,0x2f643000,0xaa1f8000,0xaf64b000,
0x3c003c00,0x3c003c00,0x3c003c00,0x3c003c00,0x3c003c00,0x3c003c00,0x3c003c00,0x3c003c00,0x80008000,0x80008000,0x80008000,0x80008000,0x80008000,0x80008000,0x80008000,0x80008000,
0x3bd93c00,0x3aa73b64,0x387239a8,0x323e361f,0xb23e0000,0xb872b61f,0xbaa7b9a8,0xbbd9bb64,0xb23e8000,0xb872b61f,0xbaa7b9a8,0xbbd9bb64,0xbbd9bc00,0xbaa7bb64,0xb872b9a8,0xb23eb61f,
0xbb64bc00,0xb61fb9a8,0x361f8000,0x3b6439a8,0x3b643c00,0x361f39a8,0xb61f0000,0xbb64b9a8,0x361f8000,0x3b6439a8,0x3b643c00,0x361f39a8,0xb61f8000,0xbb64b9a8,0xbb64bc00,0xb61fb9a8,
0x38728000,0x3bd93b64,0x323e39a8,0xbaa7b61f,0x3aa73c00,0xb23e361f,0xbbd9b9a8,0xb872bb64,0x3aa73c00,0xb23e361f,0xbbd9b9a8,0xb872bb64,0xb8728000,0xbbd9bb64,0xb23eb9a8,0x3aa7361f,
0xbc008000,0x3c008000,0xbc000000,0x3c008000,0xbc000000,0x3c008000,0xbc000000,0x3c008000,0x3c00,0x8000bc00,0x3c00,0x8000bc00,0x3c00,0x8000bc00,0x80003c00,0x8000bc00,
0xbbd98000,0x3aa7361f,0xb872b9a8,0x323e3b64,0x323ebc00,0xb8723b64,0x3aa7b9a8,0xbbd9361f,0xb23e3c00,0x3872bb64,0xbaa739a8,0x3bd9b61f,0xbbd90000,0x3aa7361f,0xb872b9a8,0x323e3b64,
0x3b648000,0xb61fb9a8,0xb61f3c00,0x3b64b9a8,0xbb648000,0x361f39a8,0x361fbc00,0xbb6439a8,0x361fbc00,0xbb6439a8,0x3b648000,0xb61fb9a8,0xb61f3c00,0x3b64b9a8,0xbb640000,0x361f39a8,
0xb8723c00,0x3bd9b61f,0xb23eb9a8,0xbaa73b64,0xbaa78000,0xb23e3b64,0x3bd9b9a8,0xb872b61f,0x3aa78000,0x323ebb64,0xbbd939a8,0x3872361f,0xb8723c00,0x3bd9b61f,0xb23eb9a8,0xbaa73b64,
0xbbd93c00,0xbaa73b64,0xb87239a8,0xb23e361f,0x323e8000,0x3872b61f,0x3aa7b9a8,0x3bd9bb64,0x323e8000,0x3872b61f,0x3aa7b9a8,0x3bd9bb64,0x3bd9bc00,0x3aa7bb64,0x3872b9a8,0x323eb61f,
0xbc003c00,0xbc003c00,0xbc003c00,0xbc003c00,0xbc003c00,0xbc003c00,0xbc003c00,0xbc003c00,0x80008000,0x80000000,0x80000000,0x80000000,0x80000000,0x80000000,0x0,0x80000000,
0xb8728000,0xbbd93b64,0xb23e39a8,0x3aa7b61f,0xbaa73c00,0x323e361f,0x3bd9b9a8,0x3872bb64,0xbaa73c00,0x323e361f,0x3bd9b9a8,0x3872bb64,0x38728000,0x3bd9bb64,0x323eb9a8,0xbaa7361f,
0x3b64bc00,0x361fb9a8,0xb61f8000,0xbb6439a8,0xbb643c00,0xb61f39a8,0x361f0000,0x3b64b9a8,0xb61f8000,0xbb6439a8,0xbb643c00,0xb61f39a8,0x361f8000,0x3b64b9a8,0x3b64bc00,0x361fb9a8,
0x3bd98000,0xbaa7361f,0x3872b9a8,0xb23e3b64,0xb23ebc00,0x38723b64,0xbaa7b9a8,0x3bd9361f,0x323e3c00,0xb872bb64,0x3aa739a8,0xbbd9b61f,0x3bd98000,0xbaa7361f,0x3872b9a8,0xb23e3b64,
0x3c008000,0xbc008000,0x3c000000,0xbc008000,0x3c000000,0xbc008000,0x3c000000,0xbc000000,0x80003c00,0xbc00,0x80003c00,0x8000bc00,0x80003c00,0xbc00,0x80003c00,0xbc00,
0x38723c00,0xbbd9b61f,0x323eb9a8,0x3aa73b64,0x3aa78000,0x323e3b64,0xbbd9b9a8,0x3872b61f,0xbaa78000,0xb23ebb64,0x3bd939a8,0xb872361f,0x38723c00,0xbbd9b61f,0x323eb9a8,0x3aa73b64,
0xbb640000,0x361fb9a8,0x361f3c00,0xbb64b9a8,0x3b648000,0xb61f39a8,0xb61fbc00,0x3b6439a8,0xb61fbc00,0x3b6439a8,0xbb640000,0x361fb9a8,0x361f3c00,0xbb64b9a8,0x3b648000,0xb61f39a8,
0x39a83c00,0xb9a80000,0xb9a8bc00,0x39a88000,0x39a83c00,0xb9a80000,0xb9a8bc00,0x39a88000,0xb9a88000,0xb9a8bc00,0x39a88000,0x39a83c00,0xb9a80000,0xb9a8bc00,0x39a88000,0x39a83c00,
0x38723c00,0xbbd9b61f,0x323eb9a8,0x3aa73b64,0xbaa70000,0xb23ebb64,0x3bd939a8,0xb872361f,0xbaa78000,0xb23ebb64,0x3bd939a8,0xb872361f,0xb872bc00,0x3bd9361f,0xb23e39a8,0xbaa7bb64,
0xb61fbc00,0x3b6439a8,0xbb640000,0x361fb9a8,0x361f3c00,0xbb64b9a8,0x3b648000,0xb61f39a8,0x3b648000,0xb61f39a8,0xb61fbc00,0x3b6439a8,0xbb648000,0x361fb9a8,0x361f3c00,0xbb64b9a8,
0x3bd98000,0xbaa7361f,0x3872b9a8,0xb23e3b64,0x323e3c00,0xb872bb64,0x3aa739a8,0xbbd9b61f,0x323e3c00,0xb872bb64,0x3aa739a8,0xbbd9b61f,0xbbd98000,0x3aa7b61f,0xb87239a8,0x323ebb64,
0xb9a88000,0xb9a83c00,0x39a88000,0x39a8bc00,0xb9a80000,0xb9a83c00,0x39a88000,0x39a8bc00,0xb9a83c00,0x39a88000,0x39a8bc00,0xb9a80000,0xb9a83c00,0x39a88000,0x39a8bc00,0xb9a88000,
0xb8728000,0xbbd93b64,0xb23e39a8,0x3aa7b61f,0x3aa7bc00,0xb23eb61f,0xbbd939a8,0xb8723b64,0xbaa73c00,0x323e361f,0x3bd9b9a8,0x3872bb64,0xb8728000,0xbbd93b64,0xb23e39a8,0x3aa7b61f,
0x361f8000,0x3b64b9a8,0x3b64bc00,0x361fb9a8,0xb61f8000,0xbb6439a8,0xbb643c00,0xb61f39a8,0x3b64bc00,0x361fb9a8,0xb61f8000,0xbb6439a8,0xbb643c00,0xb61f39a8,0x361f8000,0x3b64b9a8,
0xbbd93c00,0xbaa73b64,0xb87239a8,0xb23e361f,0xb23e8000,0xb872361f,0xbaa739a8,0xbbd93b64,0x323e8000,0x3872b61f,0x3aa7b9a8,0x3bd9bb64,0xbbd93c00,0xbaa73b64,0xb87239a8,0xb23e361f,
0xb8723c00,0x3bd9b61f,0xb23eb9a8,0xbaa73b64,0x3aa78000,0x323ebb64,0xbbd939a8,0x3872361f,0x3aa78000,0x323ebb64,0xbbd939a8,0x3872361f,0x3872bc00,0xbbd9361f,0x323e39a8,0x3aa7bb64,
0xb9a83c00,0x39a80000,0x39a8bc00,0xb9a88000,0xb9a83c00,0x39a88000,0x39a8bc00,0xb9a88000,0x39a88000,0x39a8bc00,0xb9a88000,0xb9a83c00,0x39a80000,0x39a8bc00,0xb9a88000,0xb9a83c00,
0xbbd98000,0x3aa7361f,0xb872b9a8,0x323e3b64,0xb23e3c00,0x3872bb64,0xbaa739a8,0x3bd9b61f,0xb23e3c00,0x3872bb64,0xbaa739a8,0x3bd9b61f,0x3bd98000,0xbaa7b61f,0x387239a8,0xb23ebb64,
0x361fbc00,0xbb6439a8,0x3b640000,0xb61fb9a8,0xb61f3c00,0x3b64b9a8,0xbb648000,0x361f39a8,0xbb648000,0x361f39a8,0x361fbc00,0xbb6439a8,0x3b648000,0xb61fb9a8,0xb61f3c00,0x3b64b9a8,
0x38728000,0x3bd93b64,0x323e39a8,0xbaa7b61f,0xbaa7bc00,0x323eb61f,0x3bd939a8,0x38723b64,0x3aa73c00,0xb23e361f,0xbbd9b9a8,0xb872bb64,0x38728000,0x3bd93b64,0x323e39a8,0xbaa7b61f,
0x39a88000,0x39a83c00,0xb9a88000,0xb9a8bc00,0x39a80000,0x39a83c00,0xb9a80000,0xb9a8bc00,0x39a83c00,0xb9a88000,0xb9a8bc00,0x39a88000,0x39a83c00,0xb9a88000,0xb9a8bc00,0x39a80000,
0x3bd93c00,0x3aa73b64,0x387239a8,0x323e361f,0x323e8000,0x3872361f,0x3aa739a8,0x3bd93b64,0xb23e8000,0xb872b61f,0xbaa7b9a8,0xbbd9bb64,0x3bd93c00,0x3aa73b64,0x387239a8,0x323e361f,
0xb61f8000,0xbb64b9a8,0xbb64bc00,0xb61fb9a8,0x361f8000,0x3b6439a8,0x3b643c00,0x361f39a8,0xbb64bc00,0xb61fb9a8,0x361f0000,0x3b6439a8,0x3b643c00,0x361f39a8,0xb61f8000,0xbb64b9a8,
0x0,0x0,0x0,0x0,0x0,0x0,0x0,0x0,0x3c003c00,0x3c003c00,0x3c003c00,0x3c003c00,0x3c003c00,0x3c003c00,0x3c003c00,0x3c003c00,
0x323e0000,0x3872361f,0x3aa739a8,0x3bd93b64,0x3bd93c00,0x3aa73b64,0x387239a8,0x323e361f,0x3bd93c00,0x3aa73b64,0x387239a8,0x323e361f,0xb23e0000,0xb872b61f,0xbaa7b9a8,0xbbd9bb64,
0xb61f0000,0xbb64b9a8,0xbb64bc00,0xb61fb9a8,0x361f0000,0x3b6439a8,0x3b643c00,0x361f39a8,0xbb64bc00,0xb61fb9a8,0x361f8000,0x3b6439a8,0x3b643c00,0x361f39a8,0xb61f0000,0xbb64b9a8,
0xbaa7bc00,0x323eb61f,0x3bd939a8,0x38723b64,0x38720000,0x3bd93b64,0x323e39a8,0xbaa7b61f,0x38728000,0x3bd93b64,0x323e39a8,0xbaa7b61f,0x3aa73c00,0xb23e361f,0xbbd9b9a8,0xb872bb64,
0x3c00,0x8000bc00,0x3c00,0x8000bc00,0x3c00,0x8000bc00,0x80003c00,0x8000bc00,0x3c000000,0xbc000000,0x3c008000,0xbc000000,0x3c008000,0xbc000000,0x3c008000,0xbc000000,
0xb23e3c00,0x3872bb64,0xbaa739a8,0x3bd9b61f,0xbbd90000,0x3aa7361f,0xb872b9a8,0x323e3b64,0x3bd90000,0xbaa7b61f,0x387239a8,0xb23ebb64,0xb23e3c00,0x3872bb64,0xbaa739a8,0x3bd9b61f,
0x361fbc00,0xbb6439a8,0x3b648000,0xb61fb9a8,0xb61f3c00,0x3b64b9a8,0xbb640000,0x361f39a8,0xbb640000,0x361f39a8,0x361fbc00,0xbb6439a8,0x3b640000,0xb61fb9a8,0xb61f3c00,0x3b64b9a8,
0x3aa78000,0x323ebb64,0xbbd939a8,0x3872361f,0xb8723c00,0x3bd9b61f,0xb23eb9a8,0xbaa73b64,0x3872bc00,0xbbd9361f,0x323e39a8,0x3aa7bb64,0x3aa70000,0x323ebb64,0xbbd939a8,0x3872361f,
0xb23e0000,0xb872361f,0xbaa739a8,0xbbd93b64,0xbbd93c00,0xbaa73b64,0xb87239a8,0xb23e361f,0xbbd93c00,0xbaa73b64,0xb87239a8,0xb23e361f,0x323e8000,0x3872b61f,0x3aa7b9a8,0x3bd9bb64,
0x0,0x8000,0x8000,0x8000,0x8000,0x8000,0x80008000,0x8000,0xbc003c00,0xbc003c00,0xbc003c00,0xbc003c00,0xbc003c00,0xbc003c00,0xbc003c00,0xbc003c00,
0x3aa7bc00,0xb23eb61f,0xbbd939a8,0xb8723b64,0xb8720000,0xbbd93b64,0xb23e39a8,0x3aa7b61f,0xb8728000,0xbbd93b64,0xb23e39a8,0x3aa7b61f,0xbaa73c00,0x323e361f,0x3bd9b9a8,0x3872bb64,
0x361f0000,0x3b64b9a8,0x3b64bc00,0x361fb9a8,0xb61f0000,0xbb6439a8,0xbb643c00,0xb61f39a8,0x3b64bc00,0x361fb9a8,0xb61f8000,0xbb6439a8,0xbb643c00,0xb61f39a8,0x361f0000,0x3b64b9a8,
0x323e3c00,0xb872bb64,0x3aa739a8,0xbbd9b61f,0x3bd98000,0xbaa7361f,0x3872b9a8,0xb23e3b64,0xbbd90000,0x3aa7b61f,0xb87239a8,0x323ebb64,0x323e3c00,0xb872bb64,0x3aa739a8,0xbbd9b61f,
0x80003c00,0xbc00,0x80003c00,0x8000bc00,0x80003c00,0xbc00,0x80003c00,0xbc00,0xbc000000,0x3c000000,0xbc008000,0x3c000000,0xbc008000,0x3c000000,0xbc008000,0x3c008000,
0xbaa78000,0xb23ebb64,0x3bd939a8,0xb872361f,0x38723c00,0xbbd9b61f,0x323eb9a8,0x3aa73b64,0xb872bc00,0x3bd9361f,0xb23e39a8,0xbaa7bb64,0xbaa70000,0xb23ebb64,0x3bd939a8,0xb872361f,
0xb61fbc00,0x3b6439a8,0xbb640000,0x361fb9a8,0x361f3c00,0xbb64b9a8,0x3b648000,0xb61f39a8,0x3b648000,0xb61f39a8,0xb61fbc00,0x3b6439a8,0xbb640000,0x361fb9a8,0x361f3c00,0xbb64b9a8,
0x39a80000,0x39a83c00,0xb9a80000,0xb9a8bc00,0x39a88000,0x39a83c00,0xb9a80000,0xb9a8bc00,0x39a83c00,0xb9a80000,0xb9a8bc00,0x39a88000,0x39a83c00,0xb9a80000,0xb9a8bc00,0x39a88000,
0x3aa70000,0x323e3b64,0xbbd9b9a8,0x3872b61f,0x38723c00,0xbbd9b61f,0x323eb9a8,0x3aa73b64,0x38723c00,0xbbd9b61f,0x323eb9a8,0x3aa73b64,0xbaa70000,0xb23ebb64,0x3bd939a8,0xb872361f,
0xbb640000,0x361fb9a8,0x361f3c00,0xbb64b9a8,0x3b640000,0xb61f39a8,0xb61fbc00,0x3b6439a8,0xb61fbc00,0x3b6439a8,0xbb640000,0x361fb9a8,0x361f3c00,0xbb64b9a8,0x3b648000,0xb61f39a8,
0xb23ebc00,0x38723b64,0xbaa7b9a8,0x3bd9361f,0x3bd90000,0xbaa7361f,0x3872b9a8,0xb23e3b64,0x3bd98000,0xbaa7361f,0x3872b9a8,0xb23e3b64,0x323e3c00,0xb872bb64,0x3aa739a8,0xbbd9b61f,
0xb9a83c00,0x39a88000,0x39a8bc00,0xb9a80000,0xb9a83c00,0x39a88000,0x39a8bc00,0xb9a88000,0x39a80000,0x39a8bc00,0xb9a80000,0xb9a83c00,0x39a88000,0x39a8bc00,0xb9a80000,0xb9a83c00,
0xbaa73c00,0x323e361f,0x3bd9b9a8,0x3872bb64,0xb8728000,0xbbd93b64,0xb23e39a8,0x3aa7b61f,0x38720000,0x3bd9bb64,0x323eb9a8,0xbaa7361f,0xbaa73c00,0x323e361f,0x3bd9b9a8,0x3872bb64,
0x3b64bc00,0x361fb9a8,0xb61f8000,0xbb6439a8,0xbb643c00,0xb61f39a8,0x361f8000,0x3b64b9a8,0xb61f0000,0xbb6439a8,0xbb643c00,0xb61f39a8,0x361f0000,0x3b64b9a8,0x3b64bc00,0x361fb9a8,
0x323e8000,0x3872b61f,0x3aa7b9a8,0x3bd9bb64,0xbbd93c00,0xbaa73b64,0xb87239a8,0xb23e361f,0x3bd9bc00,0x3aa7bb64,0x3872b9a8,0x323eb61f,0x323e0000,0x3872b61f,0x3aa7b9a8,0x3bd9bb64,
0xbaa70000,0xb23e3b64,0x3bd9b9a8,0xb872b61f,0xb8723c00,0x3bd9b61f,0xb23eb9a8,0xbaa73b64,0xb8723c00,0x3bd9b61f,0xb23eb9a8,0xbaa73b64,0x3aa78000,0x323ebb64,0xbbd939a8,0x3872361f,
0xb9a80000,0xb9a83c00,0x39a80000,0x39a8bc00,0xb9a88000,0xb9a83c00,0x39a80000,0x39a8bc00,0xb9a83c00,0x39a80000,0x39a8bc00,0xb9a88000,0xb9a83c00,0x39a88000,0x39a8bc00,0xb9a88000,
0x323ebc00,0xb8723b64,0x3aa7b9a8,0xbbd9361f,0xbbd90000,0x3aa7361f,0xb872b9a8,0x323e3b64,0xbbd98000,0x3aa7361f,0xb872b9a8,0x323e3b64,0xb23e3c00,0x3872bb64,0xbaa739a8,0x3bd9b61f,
0x3b640000,0xb61fb9a8,0xb61f3c00,0x3b64b9a8,0xbb640000,0x361f39a8,0x361fbc00,0xbb6439a8,0x361fbc00,0xbb6439a8,0x3b640000,0xb61fb9a8,0xb61f3c00,0x3b64b9a8,0xbb648000,0x361f39a8,
0x3aa73c00,0xb23e361f,0xbbd9b9a8,0xb872bb64,0x38728000,0x3bd93b64,0x323e39a8,0xbaa7b61f,0xb8720000,0xbbd9bb64,0xb23eb9a8,0x3aa7361f,0x3aa73c00,0xb23e361f,0xbbd9b9a8,0xb872bb64,
0x39a83c00,0xb9a88000,0xb9a8bc00,0x39a88000,0x39a83c00,0xb9a88000,0xb9a8bc00,0x39a80000,0xb9a80000,0xb9a8bc00,0x39a80000,0x39a83c00,0xb9a88000,0xb9a8bc00,0x39a88000,0x39a83c00,
0xb23e8000,0xb872b61f,0xbaa7b9a8,0xbbd9bb64,0x3bd93c00,0x3aa73b64,0x387239a8,0x323e361f,0xbbd9bc00,0xbaa7bb64,0xb872b9a8,0xb23eb61f,0xb23e0000,0xb872b61f,0xbaa7b9a8,0xbbd9bb64,
0xbb64bc00,0xb61fb9a8,0x361f0000,0x3b6439a8,0x3b643c00,0x361f39a8,0xb61f8000,0xbb64b9a8,0x361f0000,0x3b6439a8,0x3b643c00,0x361f39a8,0xb61f0000,0xbb64b9a8,0xbb64bc00,0xb61fb9a8,
};
__device__ __align__(1024) bf16 g_x1T[DM * XP];
__device__ __align__(1024) bf16 g_x2T[DM * XP];
__device__ __align__(1024) unsigned g_xcnt[10][4][32];
__device__ __align__(1024) uint4 g_of[8][16][1280];
__device__ __align__(1024) float g_fs[2][SEQ];

#define TS_SMEM 0
#define TS_DECL
#define TS_ARG
#define TS_PASS
#define TS_PHASE(p)
#define TS(i)
#define TSX(row, i)
#define TS_BEGIN
#define TS_END

struct cplx { float r, i; };
__device__ __forceinline__ cplx cmul(cplx a, cplx b) {
    cplx o;
    o.r = fmaf(a.r, b.r, -a.i * b.i);
    o.i = fmaf(a.r, b.i, a.i * b.r);
    return o;
}
__device__ __forceinline__ cplx csq(cplx a) {
    cplx o;
    o.r = fmaf(a.r, a.r, -a.i * a.i);
    o.i = 2.f * a.r * a.i;
    return o;
}
__device__ __forceinline__ cplx cexp_p(float arl, float ai, float p) {
    float mag = ex2(arl * p);
    float ang = ai * p;
    float n = rintf(ang * 0.15915494309189535f);
    float r = fmaf(n, -6.2831854820251465f, ang);
    r = fmaf(n, 1.7484555e-7f, r);
    cplx o;
    o.r = mag * __cosf(r);
    o.i = mag * __sinf(r);
    return o;
}

__device__ __forceinline__ uint32_t pack2h(float lo, float hi) {
    uint32_t r;
    asm("cvt.rn.f16x2.f32 %0, %1, %2;" : "=r"(r) : "f"(hi), "f"(lo));
    return r;
}
__device__ __forceinline__ uint32_t hmul(uint32_t a, uint32_t b) { uint32_t d; asm("mul.rn.f16x2 %0, %1, %2;" : "=r"(d) : "r"(a), "r"(b)); return d; }
__device__ __forceinline__ uint32_t hfma(uint32_t a, uint32_t b, uint32_t c) { uint32_t d; asm("fma.rn.f16x2 %0, %1, %2, %3;" : "=r"(d) : "r"(a), "r"(b), "r"(c)); return d; }
__device__ __forceinline__ uint32_t hfms(uint32_t a, uint32_t b, uint32_t c) {
    uint32_t d;
    asm("{\n.reg .b32 n;\nneg.f16x2 n, %1;\nfma.rn.f16x2 %0, n, %2, %3;\n}" : "=r"(d) : "r"(a), "r"(b), "r"(c));
    return d;
}
__device__ __forceinline__ uint32_t hadd(uint32_t a, uint32_t b) { uint32_t d; asm("add.rn.f16x2 %0, %1, %2;" : "=r"(d) : "r"(a), "r"(b)); return d; }
__device__ __forceinline__ uint32_t hsub(uint32_t a, uint32_t b) { uint32_t d; asm("sub.rn.f16x2 %0, %1, %2;" : "=r"(d) : "r"(a), "r"(b)); return d; }
__device__ __forceinline__ uint4 ldg_tab(int tab, int t) { return ldg128((const uint4*)c_fft + t + tab * 128); }
__device__ __forceinline__ uint32_t u4(const uint4& v, int i) { return i == 0 ? v.x : i == 1 ? v.y : i == 2 ? v.z : v.w; }
struct cpair { uint32_t r, i; };
__device__ __forceinline__ cpair pmul(cpair p, uint32_t z) {
    const __half2 zv = *reinterpret_cast<const __half2*>(&z), pr = *reinterpret_cast<const __half2*>(&p.r), pi = *reinterpret_cast<const __half2*>(&p.i);
    const __half2 zr = __low2half2(zv), zi = __high2half2(zv);
    const __half2 a = __hfma2(__hneg2(pi), zi, __hmul2(pr, zr)), b = __hfma2(pi, zr, __hmul2(pr, zi));
    return {*reinterpret_cast<const uint32_t*>(&a), *reinterpret_cast<const uint32_t*>(&b)};
}
__device__ __forceinline__ uint32_t packz(cplx z) { return pack2h(z.r, z.i); }
__device__ __forceinline__ void wgmma_kg(float (&d)[24], uint64_t da, uint64_t db, int scale_d) {
    asm volatile("{\n.reg .pred p;\nsetp.ne.b32 p, %26, 0;\n"
                 "wgmma.mma_async.sync.aligned.m64n48k16.f32.f16.f16 "
                 "{%0,%1,%2,%3,%4,%5,%6,%7,%8,%9,%10,%11,%12,%13,%14,%15,%16,%17,%18,%19,%20,%21,%22,%23}, %24, %25, p, 1, 1, 1, 1;\n}\n"
                 : "+f"(d[0]), "+f"(d[1]), "+f"(d[2]), "+f"(d[3]), "+f"(d[4]), "+f"(d[5]), "+f"(d[6]), "+f"(d[7]), "+f"(d[8]), "+f"(d[9]),
                   "+f"(d[10]), "+f"(d[11]), "+f"(d[12]), "+f"(d[13]), "+f"(d[14]), "+f"(d[15]), "+f"(d[16]), "+f"(d[17]), "+f"(d[18]), "+f"(d[19]),
                   "+f"(d[20]), "+f"(d[21]), "+f"(d[22]), "+f"(d[23])
                 : "l"(da), "l"(db), "r"(scale_d));
}

struct SsmParams { const bf16 *lar, *aim, *cre, *cim, *logdt, *dskip; const unsigned* epoch; };
constexpr int KG_TABLES = 6 * 16384, KG_RES = 1664;
struct KgShared { uint32_t kmax[6], kexp[6]; float cinv[6], tap0[6]; };
#define KS(f, i) (ks + (uint32_t)offsetof(KgShared, f) + 4 * (i))
struct KgParams { uint32_t l[3], a[3], r[3], i[3], dt, ds; };

__device__ __forceinline__ int cta_channel(int bx, int i) { return i < 2 ? 2 * bx + i : i < 4 ? 382 + 2 * bx + i : 256 + bx; }
__device__ __forceinline__ bool kg_is_hi(int warp) { return ((warp >> 1) ^ (warp >> 2)) & 1; }
__device__ __forceinline__ void kgen_load(KgParams& kp, int bx, int warp, int lane, const SsmParams& sp) {
    const int d = cta_channel(bx, 2 * (warp >> 2) + (warp & 1)), idx = d * (NMODE / 2) + lane;
    const bf16 *pr = kg_is_hi(warp) ? sp.cre : sp.lar, *pi = kg_is_hi(warp) ? sp.cim : sp.aim;
    kp.dt = __ldg((const uint16_t*)sp.logdt + d);
#pragma unroll
    for (int j = 0; j < 3; j++) {
        kp.l[j] = __ldg((const uint32_t*)sp.lar + idx + 32 * j); kp.a[j] = __ldg((const uint32_t*)sp.aim + idx + 32 * j);
        kp.r[j] = __ldg((const uint32_t*)pr + idx + 32 * j); kp.i[j] = __ldg((const uint32_t*)pi + idx + 32 * j);
    }
    kp.ds = __ldg((const uint16_t*)sp.dskip + cta_channel(bx, warp >> 1));
}

struct KgAnchors { uint32_t v[8]; };
__device__ __forceinline__ KgAnchors kg_anchor_lo(const KgParams& kp, uint32_t sel, float dt) {
    auto B = [&](uint32_t v) { return __uint_as_float(__byte_perm(v, 0u, sel)); };
    const float arl = -rbf(ex2(B(kp.l[0]) * 1.4426950408889634f)) * dt * 1.4426950408889634f, ai = B(kp.a[0]) * dt;
    const cplx z8 = cexp_p(arl, ai, 8.f), z16 = csq(z8), z24 = cmul(z16, z8), z32 = csq(z16), z64 = csq(z32), z128 = csq(z64), z192 = cmul(z128, z64);
    return {{pack2h(1.f, z8.r), pack2h(0.f, z8.i), pack2h(z16.r, z24.r), pack2h(z16.i, z24.i), packz(z32), packz(z64), packz(z128), packz(z192)}};
}
__device__ __forceinline__ KgAnchors kg_anchor_hi(const KgParams& kp, uint32_t sel, float dt, float cs) {
    auto B = [&](uint32_t v) { return __uint_as_float(__byte_perm(v, 0u, sel)); };
    const float arl = -rbf(ex2(B(kp.l[0]) * 1.4426950408889634f)) * dt * 1.4426950408889634f, ai = B(kp.a[0]) * dt;
    const cplx z1 = cexp_p(arl, -ai, 1.f), z2 = csq(z1), z4 = csq(z2), z256 = cexp_p(arl, -ai, 256.f), z512 = csq(z256), z1024 = csq(z512);
    const cplx H0 = {B(kp.r[0]) * cs, -B(kp.i[0]) * cs}, H4 = cmul(H0, z4);
    return {{pack2h(H0.r, H4.r), pack2h(H0.i, H4.i), packz(z1), packz(z2), packz(z256), packz(z512), packz(z1024), 0u}};
}

template <class Idle>
__device__ __forceinline__ void kgen_tables(KgParams& kp, uint32_t scr, uint32_t dump, uint32_t ks, int warp, int lane, Idle idle TS_ARG) {
    const int wg = warp >> 2, half = warp & 1, sw = lane & 7;
    const bool hi = kg_is_hi(warp);
    TS(23);
    const float dt = rbf(ex2(bf_lo(kp.dt) * 1.4426950408889634f));
    uint32_t sel = (wg == 2 && half) ? 0x3244u : 0x1044u;
    float cs = 0.f;
    KgAnchors an;
    if (hi) {
        uint32_t m = 0;
#pragma unroll
        for (int j = 0; j < 3; j++) m = __vmaxu2(m, __vmaxu2(kp.r[j] & 0x7FFF7FFFu, kp.i[j] & 0x7FFF7FFFu));
        m = __reduce_max_sync(~0u, max(m << 16, m & 0xFFFF0000u));
        const uint32_t e = min(max(__float_as_uint(2.f * dt * __uint_as_float(m)) >> 23, 2u), 252u);
        cs = 2.f * dt * __uint_as_float((253u - e) << 23);
        if (lane == 0) { sts32(KS(cinv, 2 * wg + half), (e + 1u) << 23); sts32(KS(kmax, 2 * wg + half), 0u); }
        an = kg_anchor_hi(kp, sel, dt, cs);
    } else {
        an = kg_anchor_lo(kp, sel, dt);
    }
    float acc[24];
#pragma unroll
    for (int i = 0; i < 24; i++) acc[i] = 0.f;
    uint32_t tb = scr + 2 * wg * 16384 + lane * 128;
    uint64_t da = mkdesc(scr + 2 * wg * 16384, 4096, 1024, 1);
    int flip = 16384;
#pragma unroll 1
    for (int c = wg == 2 ? 1 : 0, step = wg == 2 ? 2 : 1; c < 6; c += step) {
        if (wg < 2) sel ^= 0x2200u;
        if (!hi) {
            if (c & 1) { kp.l[0] = kp.l[1]; kp.l[1] = kp.l[2]; kp.a[0] = kp.a[1]; kp.a[1] = kp.a[2]; }
            cpair p[4];
            p[0] = {an.v[0], an.v[1]}; p[1] = {an.v[2], an.v[3]};
            p[2] = pmul(p[0], an.v[4]); p[3] = pmul(p[1], an.v[4]);
#pragma unroll
            for (int j = 0; j < 4; j++) {
                cpair v[4];
#pragma unroll
                for (int i = 0; i < 4; i++) v[i] = j ? pmul(p[i], an.v[4 + j]) : p[i];
                const uint32_t a = tb + (((4 * half + j) ^ sw) << 4);
                sts128(a, make_uint4(v[0].r, v[1].r, v[2].r, v[3].r));
                sts128(a + 4096, make_uint4(v[0].i, v[1].i, v[2].i, v[3].i));
            }
            an = kg_anchor_lo(kp, sel, dt);
        } else {
            if (c & 1) {
#pragma unroll
                for (int j = 0; j < 2; j++) { kp.l[j] = kp.l[j + 1]; kp.a[j] = kp.a[j + 1]; kp.r[j] = kp.r[j + 1]; kp.i[j] = kp.i[j + 1]; }
            }
            const uint32_t h1 = an.v[2], h2 = an.v[3], h256 = an.v[4], h512 = an.v[5], h1024 = an.v[6];
            cpair p[11];
            p[0] = {an.v[0], an.v[1]};
            p[1] = pmul(p[0], h2); p[2] = pmul(p[0], h1); p[3] = pmul(p[1], h1);
            p[4] = pmul(p[0], h256); p[5] = pmul(p[1], h256); p[6] = pmul(p[0], h512); p[7] = pmul(p[4], h512);
            p[8] = pmul({__byte_perm(p[0].r, p[4].r, 0x5410), __byte_perm(p[0].i, p[4].i, 0x5410)}, h1024);
            p[9] = pmul(p[8], h512); p[10] = pmul(p[8], h1024);
#pragma unroll
            for (int j = 0; j < 3; j++) {
                const uint32_t a = tb + 8192 + (((3 * half + j) ^ sw) << 4);
                sts128(a, make_uint4(p[4 * j].r, p[4 * j + 1].r, p[4 * j + 2].r, p[j < 2 ? 4 * j + 3 : 10].r));
                sts128(a + 4096, make_uint4(p[4 * j].i, p[4 * j + 1].i, p[4 * j + 2].i, p[j < 2 ? 4 * j + 3 : 10].i));
            }
            an = kg_anchor_hi(kp, sel, dt, cs);
        }
        if (c == 0) TS(24);
        if (c == 3) TS(25);
        fence_async_smem();
        wg_wait<0>();
        named_bar(5 + wg, 128);
        wg_fence();
#pragma unroll
        for (int k = 0; k < 4; k++) wgmma_kg(acc, da + k * 128, da + 512 + k * 128, 1);
        wg_commit();
        tb += flip; da += flip >> 4; flip = -flip;
    }
    const bool up = warp & 2;
    const int r = 2 * wg + up, lo0 = 16 * half + (lane >> 2);
    const uint32_t o = dump + r * KG_RES + lo0 * 52 + 4 * (lane & 3);
    const float ci = __uint_as_float(lds32(KS(cinv, r)));
    const float ds = warp <= 8 ? bf_lo(kp.ds) : 0.f;
    TS(26);
    idle();
    wg_wait<0>();
    float v[12], m = 0.f;
#pragma unroll
    for (int j = 0; j < 12; j++) { v[j] = up ? acc[12 + j] : acc[j]; m = fmaxf(m, fabsf(v[j])); }
#pragma unroll
    for (int j = 0; j < 6; j++) sts32(o + (j & 1) * 416 + (j >> 1) * 16, pack2h(v[2 * j], v[2 * j + 1]));
    const uint32_t mm = __reduce_max_sync(~0u, __float_as_uint(m));
    if (lane == 0) {
        asm volatile("red.shared.max.u32 [%0], %1;" ::"r"(KS(kmax, r)), "r"(mm) : "memory");
        if (!half) sts32(KS(tap0, r), __float_as_uint(fmaf(ci, v[0], ds)));
    }
}
#define F_STAG 4
__device__ __forceinline__ void wgmma_h64_rs(uint32_t (&d)[16], const uint4& a, uint64_t db, int scale_d) {
    asm volatile("{\n.reg .pred p;\nsetp.ne.b32 p, %21, 0;\n"
                 "wgmma.mma_async.sync.aligned.m64n64k16.f16.f16.f16 {%0,%1,%2,%3,%4,%5,%6,%7,%8,%9,%10,%11,%12,%13,%14,%15}, {%16,%17,%18,%19}, %20, p, 1, 1, 1;\n}\n"
                 : "+r"(d[0]), "+r"(d[1]), "+r"(d[2]), "+r"(d[3]), "+r"(d[4]), "+r"(d[5]), "+r"(d[6]), "+r"(d[7]), "+r"(d[8]), "+r"(d[9]),
                   "+r"(d[10]), "+r"(d[11]), "+r"(d[12]), "+r"(d[13]), "+r"(d[14]), "+r"(d[15])
                 : "r"(a.x), "r"(a.y), "r"(a.z), "r"(a.w), "l"(db), "r"(scale_d));
}
template <int TB>
__device__ __forceinline__ void wgmma_h32_rs(uint32_t (&d)[8], const uint4& a, uint64_t db, int scale_d) {
    asm volatile("{\n.reg .pred p;\nsetp.ne.b32 p, %13, 0;\n"
                 "wgmma.mma_async.sync.aligned.m64n32k16.f16.f16.f16 {%0,%1,%2,%3,%4,%5,%6,%7}, {%8,%9,%10,%11}, %12, p, 1, 1, %14;\n}\n"
                 : "+r"(d[0]), "+r"(d[1]), "+r"(d[2]), "+r"(d[3]), "+r"(d[4]), "+r"(d[5]), "+r"(d[6]), "+r"(d[7])
                 : "r"(a.x), "r"(a.y), "r"(a.z), "r"(a.w), "l"(db), "r"(scale_d), "n"(TB));
}
__device__ __forceinline__ void wgmma_s1(uint32_t (&d)[16], const uint4& a, uint64_t db, int scale_d) { wgmma_h64_rs(d, a, db, scale_d); }
__device__ __forceinline__ void wgmma_s1(uint32_t (&d)[8], const uint4& a, uint64_t db, int scale_d) { wgmma_h32_rs<1>(d, a, db, scale_d); }
__device__ __forceinline__ void wgmma_s4(float (&d)[32], const uint4& a, uint64_t db, uint32_t meta, int scale_d) {
    asm volatile("{\n.reg .pred p;\nsetp.ne.b32 p, %38, 0;\n"
                 "wgmma.mma_async.sp.sync.aligned.m64n64k32.f32.f16.f16 {%0,%1,%2,%3,%4,%5,%6,%7,%8,%9,%10,%11,%12,%13,%14,%15,%16,%17,%18,%19,%20,%21,%22,%23,%24,%25,%26,%27,%28,%29,%30,%31}, {%32,%33,%34,%35}, %36, %37, 0, p, 1, 1, 1;\n}\n"
                 : "+f"(d[0]), "+f"(d[1]), "+f"(d[2]), "+f"(d[3]), "+f"(d[4]), "+f"(d[5]), "+f"(d[6]), "+f"(d[7]), "+f"(d[8]), "+f"(d[9]), "+f"(d[10]), "+f"(d[11]), "+f"(d[12]), "+f"(d[13]), "+f"(d[14]), "+f"(d[15]), "+f"(d[16]), "+f"(d[17]), "+f"(d[18]), "+f"(d[19]), "+f"(d[20]), "+f"(d[21]), "+f"(d[22]), "+f"(d[23]), "+f"(d[24]), "+f"(d[25]), "+f"(d[26]), "+f"(d[27]), "+f"(d[28]), "+f"(d[29]), "+f"(d[30]), "+f"(d[31])
                 : "r"(a.x), "r"(a.y), "r"(a.z), "r"(a.w), "l"(db), "r"(meta), "r"(scale_d));
}
__device__ __forceinline__ void wgmma_s4(float (&d)[16], const uint4& a, uint64_t db, uint32_t meta, int scale_d) {
    asm volatile("{\n.reg .pred p;\nsetp.ne.b32 p, %22, 0;\n"
                 "wgmma.mma_async.sp.sync.aligned.m64n32k32.f32.f16.f16 {%0,%1,%2,%3,%4,%5,%6,%7,%8,%9,%10,%11,%12,%13,%14,%15}, {%16,%17,%18,%19}, %20, %21, 0, p, 1, 1, 1;\n}\n"
                 : "+f"(d[0]), "+f"(d[1]), "+f"(d[2]), "+f"(d[3]), "+f"(d[4]), "+f"(d[5]), "+f"(d[6]), "+f"(d[7]), "+f"(d[8]), "+f"(d[9]), "+f"(d[10]), "+f"(d[11]), "+f"(d[12]), "+f"(d[13]), "+f"(d[14]), "+f"(d[15])
                 : "r"(a.x), "r"(a.y), "r"(a.z), "r"(a.w), "l"(db), "r"(meta), "r"(scale_d));
}

__device__ __forceinline__ uint32_t& u4r(uint4& v, int i) { return i == 0 ? v.x : i == 1 ? v.y : i == 2 ? v.z : v.w; }

template <int NC>
__device__ __forceinline__ void fft_stage(const uint32_t (&u)[2][4], int c, uint32_t eo, int w, int lane) {
    const int mi = lane >> 3, mj = lane & 7;
    const uint32_t a = eo + (8 * w + mj) * 128 + (((4 * c + mi) ^ mj) << 4);
    stsm_x4(a, hadd(u[0][0], u[1][0]), hadd(u[0][1], u[1][1]), hadd(u[0][2], u[1][2]), hadd(u[0][3], u[1][3]));
    stsm_x4(NC == 2 ? a + 4096 : a ^ 64, hsub(u[0][0], u[1][0]), hsub(u[0][1], u[1][1]), hsub(u[0][2], u[1][2]), hsub(u[0][3], u[1][3]));
}
template <int NC>
__device__ __forceinline__ void kernel_stage(const uint4 (&ko)[2], uint32_t kt, uint32_t ks, int r, uint32_t eo, int w, int lane) {
    uint32_t u[2][2][4], sc[NC], t0[NC];
#pragma unroll
    for (int c = 0; c < NC; c++) {
        auto L = [](uint32_t a) { return __uint_as_float(lds32(a)); };
        const float ci = L(KS(cinv, r + c)), k0 = L(KS(tap0, r + c)) + (NC == 1 ? L(KS(tap0, r + 1)) : 0.f);
        const float mx = fmaxf(ci * (L(KS(kmax, r + c)) + (NC == 1 ? L(KS(kmax, r + 1)) : 0.f) + 0x1p-14f), fabsf(k0));
        const uint32_t e = min(max(__float_as_uint(mx) >> 23, 4u), 250u);
        const float s = __uint_as_float((253u - e) << 23), f = s * ci;
        if (w == 0 && lane == 0) sts32(KS(kexp, r + c), e);
        sc[c] = pack2h(f, f); t0[c] = pack2h(k0 * s, 0.f);
    }
#pragma unroll
    for (int h = 0; h < 2; h++)
#pragma unroll
        for (int j = 0; j < 4; j++) {
            const uint32_t a0 = kt + (u4(ko[h], j) & 0xFFFF), a1 = kt + (u4(ko[h], j) >> 16);
#pragma unroll
            for (int c = 0; c < 2; c++)
                asm volatile("{\n.reg .b16 a, b;\nld.shared.b16 a, [%1];\nld.shared.b16 b, [%2];\nmov.b32 %0, {a, b};\n}"
                             : "=r"(u[c][h][j]) : "r"(a0 + c * KG_RES), "r"(a1 + c * KG_RES) : "memory");
            if (NC == 1) u[0][h][j] = hadd(u[0][h][j], u[1][h][j]);
#pragma unroll
            for (int c = 0; c < NC; c++) {
                u[c][h][j] = hmul(u[c][h][j], sc[c]);
                if (h + j == 0 && w == 0 && lane == 0) u[c][0][0] = __byte_perm(t0[c], u[c][0][0], 0x7610);
            }
        }
#pragma unroll
    for (int c = 0; c < NC; c++) fft_stage<NC>(u[c], c, eo, w, lane);
}

template <int NC, bool SHEAR, class Mid>
__device__ __forceinline__ void fft_forward(const uint4 (&a1)[4], const uint4 (&tw)[4], uint32_t eo, uint32_t s2, uint32_t (&X)[NC][2][8], Mid mid) {
    uint32_t dr[8 * NC], di[8 * NC];
    const uint64_t de = mkdesc(eo, 4096, 1024, 1), d2 = mkdesc(s2, 16, 1024, 1);
    wg_fence();
    wgmma_s1(dr, a1[0], de, 0);
    wgmma_s1(di, a1[2], de + (NC == 2 ? 256 : 4), 0);
    wgmma_s1(dr, a1[1], de + 128, 1);
    wgmma_s1(di, a1[3], de + (NC == 2 ? 384 : 132), 1);
    wg_commit();
    mid();
    wg_wait<0>();
#pragma unroll
    for (int c = 0; c < NC; c++) {
        uint4 zr[2], zi[2];
#pragma unroll
        for (int p = 0; p < 2; p++)
#pragma unroll
            for (int i = 0; i < 4; i++) {
                const uint32_t r = dr[8 * c + 4 * p + i], m = di[8 * c + 4 * p + i], tr = u4(tw[p], i), ti = u4(tw[2 + p], i);
                if (SHEAR) {
                    const uint32_t r1 = hfma(tr, m, r), m1 = hfma(ti, r1, m);
                    u4r(zr[p], i) = hfma(tr, m1, r1); u4r(zi[p], i) = m1;
                } else {
                    u4r(zr[p], i) = hfms(m, ti, hmul(r, tr));
                    u4r(zi[p], i) = hfma(m, tr, hmul(r, ti));
                }
            }
        wg_fence();
        wgmma_h32_rs<0>(X[c][0], zi[0], d2 + 2, 0);
        wgmma_h32_rs<0>(X[c][1], zi[1], d2 + 6, 0);
        wgmma_h32_rs<0>(X[c][0], zr[0], d2, 1);
        wgmma_h32_rs<0>(X[c][1], zr[1], d2 + 4, 1);
        wg_commit();
    }
}

template <int NC, class Idle, class Staged>
__device__ __forceinline__ void conv_wg(int ch0, int layer, uint32_t eo, uint32_t zb, uint32_t s23, uint32_t kexp, uint32_t epoch, uint32_t st, uint32_t sbar, uint32_t rbar, uint32_t fbar,
                                        int warp, int lane, uint4 (&a1)[4], uint4 (&tw)[4], Idle idle, Staged staged TS_ARG) {
    const int wg = warp >> 2, w = warp & 3, t = 32 * w + lane, q = lane & 3, mi = lane >> 3, mj = lane & 7;
    auto F = [](uint32_t x) { return __uint_as_float(x); };
    uint32_t KH[NC][2][8];
    TS(2);
    fft_forward<NC, false>(a1, tw, eo, s23, KH, [] {});
    named_bar(1 + wg, 128);
    uint4 a4[4];
#pragma unroll
    for (int i = 0; i < 4; i++) if (NC == 2) { tw[i] = ldg_tab(4 + i, t); a4[i] = ldg_tab(12 + i, t); }
    wg_wait<0>();
    TS(4);
    idle();
    uint2 x[NC][2][2];
    const uint32_t ra[2] = {4u * t, 4u * (t ^ 252)};
    if (w == 0) {
        const bf16* pp = g_x1T + (uint32_t)(ch0 + NC - 1) * XP + 64 * lane + 60;
        uint32_t v;
        int spin = 0;
        do { asm volatile("ld.relaxed.gpu.global.u32 %0, [%1];" : "=r"(v) : "l"(pp) : "memory"); } while (__any_sync(~0u, ~(v ^ layer) & 1u) && ++spin < (1 << 18));
        if (lane == 0) mbar_arrive(rbar);
    } else {
        mbar_wait(rbar, 0);
    }
    TS(5);
    auto xload = [&](int i) {
        const unsigned long long v = ld_ll((const unsigned long long*)(g_x1T + (uint32_t)ch0 * XP + ra[(i >> 1) & 1] + ((i >> 2) * XP + 1024 * (i & 1))));
        x[i >> 2][(i >> 1) & 1][i & 1] = make_uint2((uint32_t)v, (uint32_t)(v >> 32));
    };
#pragma unroll
    for (int i = 0; i < 4 * NC; i++) xload(i);
    TS(6);
    if (NC == 1) {
        uint4 s[8];
        TS(1);
#pragma unroll
        for (int i = 0; i < 8; i++) s[i] = make_uint4(layer, 0, 0, 0);
        int spin = 0;
        uint32_t bad;
        do {
            bad = 0;
#pragma unroll
            for (int i = 0; i < 8; i++)
                if (((s[i].x ^ layer) & 1u) == 0) s[i] = ld_ll4((const uint4*)(g_fs[0] + ra[i >> 2] + (SEQ * (i & 1) + 1024 * ((i >> 1) & 1))));
#pragma unroll
            for (int i = 0; i < 8; i++) bad |= ~(s[i].x ^ layer);
        } while ((bad & 1u) && ++spin < (1 << 18));
#pragma unroll
        for (int i = 0; i < 8; i++) sts128(st + i * 2048 + t * 16, s[i]);
        __syncwarp();
        if (lane == 0) mbar_arrive(sbar + 8 * w);
        TS(14);
    }
    for (int spin = 0; spin < (1 << 18); spin++) {
        uint32_t bad = 0;
#pragma unroll
        for (int i = 0; i < 4 * NC; i++) bad |= ~(x[i >> 2][(i >> 1) & 1][i & 1].x ^ layer);
        if (!(bad & 1u)) break;
#pragma unroll
        for (int i = 0; i < 4 * NC; i++) if (((x[i >> 2][(i >> 1) & 1][i & 1].x ^ layer) & 1u) == 0) xload(i);
    }
    __syncwarp();
#pragma unroll
    for (int i = 0; i < 4; i++) if (NC == 1) { tw[i] = ldg_tab(4 + i, t); a4[i] = ldg_tab(12 + i, t); }
    TS(26);
    if (NC == 2) mbar_wait(sbar + 8 * w, 0);
    staged();
    {
        uint4 s[2][2][2];
        uint32_t u[NC][2][4];
#pragma unroll
        for (int h = 0; h < 2; h++) {
            if (NC == 1 || h == 0) {
#pragma unroll
                for (int i = 4 * h; i < (NC == 1 ? 4 * h + 4 : 8); i++) s[i >> 2][(i >> 1) & 1][i & 1] = lds128(st + i * 2048 + t * 16);
            }
            if (h == 0) TS(7);
#pragma unroll
            for (int c = 0; c < NC; c++)
#pragma unroll
                for (int j = 0; j < 4; j++) {
                    const uint4 &a = s[h][j >> 1][0], &b = s[h][j >> 1][1];
                    const uint32_t xv = (j & 1) ? x[c][h][j >> 1].y : x[c][h][j >> 1].x;
                    u[c][h][j] = pack2h(fmaf(bf_lo(xv), F(u4(a, 2 * (j & 1))), F(u4(b, 2 * (j & 1)))), fmaf(bf_hi(xv), F(u4(a, 2 * (j & 1) + 1)), F(u4(b, 2 * (j & 1) + 1))));
                }
        }
#pragma unroll
        for (int c = 0; c < NC; c++) fft_stage<NC>(u[c], c, eo, w, lane);
    }
    TS(8);
    fence_async_smem();
    TS(9);
    named_bar(1 + wg, 128);
    uint32_t X[NC][2][8], Y[NC][2][8];
    uint32_t oscale[NC];
    fft_forward<NC, true>(a1, tw, eo, s23, X, [&] {
#pragma unroll
        for (int c = 0; c < NC; c++) oscale[c] = (lds32(kexp + 4 * c) + 3u) * 0x00800080u;
        if (layer) {
#pragma unroll
            for (int i = 0; i < 4 * NC; i++) asm volatile("mov.b32 %0, 0;\nmov.b32 %1, 0;" : "=r"(x[i >> 2][(i >> 1) & 1][i & 1].x), "=r"(x[i >> 2][(i >> 1) & 1][i & 1].y));
        }
        if (NC == 2 && wg == 1 && lane == 0) mbar_arrive(fbar);
        TS(3); if (F_STAG >= 2 && NC == 2 && wg == 1) named_bar(10 + w, 64); });
    if (F_STAG == 2 && NC == 2 && wg == 0) asm volatile("bar.arrive %0, 64;" ::"r"(10 + w) : "memory");
    TS(10);
    const uint64_t d3 = mkdesc(s23 + 4096, 16, 1024, 1);
#pragma unroll
    for (int c = 0; c < NC; c++) {
        wg_wait<NC - 1>();
        TS(11 + c);
        uint4 pr[2], pi[2];
#pragma unroll
        for (int i = 0; i < 4; i++) {
            const uint32_t er = X[c][0][i], ei = X[c][0][4 + i], orr = X[c][1][i], oi = X[c][1][4 + i];
            const uint32_t ar = KH[c][0][i], ai = KH[c][0][4 + i], br = KH[c][1][i], bi = KH[c][1][4 + i];
            u4r(pr[0], i) = hfms(bi, oi, hfma(br, orr, hfms(ai, ei, hmul(ar, er))));
            u4r(pi[0], i) = hfma(bi, orr, hfma(br, oi, hfma(ai, er, hmul(ar, ei))));
            u4r(pr[1], i) = hfms(ai, oi, hfma(ar, orr, hfms(bi, ei, hmul(br, er))));
            u4r(pi[1], i) = hfma(ai, orr, hfma(ar, oi, hfma(bi, er, hmul(br, ei))));
        }
        if (F_STAG == 3 + c && NC == 2 && wg == 0) asm volatile("bar.arrive %0, 64;" ::"r"(10 + w), "r"(pr[0].x ^ pr[1].w ^ pi[0].y ^ pi[1].z) : "memory");
        wg_fence();
        wgmma_h32_rs<0>(Y[c][0], pr[0], d3, 0);
        wgmma_h32_rs<0>(Y[c][1], pr[1], d3 + 4, 0);
        wgmma_h32_rs<0>(Y[c][0], pi[0], d3 + 2, 1);
        wgmma_h32_rs<0>(Y[c][1], pi[1], d3 + 6, 1);
        wg_commit();
    }
#pragma unroll
    for (int c = 0; c < NC; c++) {
        if (c + 1 < NC) wg_wait<1>(); else wg_wait<0>();
        TS(13 + c);
        uint32_t zr[2][4], zi[2][4];
#pragma unroll
        for (int p = 0; p < 2; p++)
#pragma unroll
            for (int i = 0; i < 4; i++) {
                const uint32_t r = Y[c][p][i], m = Y[c][p][4 + i], tr = u4(tw[p], i), ti = u4(tw[2 + p], i);
                const uint32_t r1 = hfms(tr, m, r), m1 = hfms(ti, r1, m);
                zr[i & 1][2 * p + (i >> 1)] = hfms(tr, m1, r1);
                zi[i & 1][2 * p + (i >> 1)] = m1;
            }
        const int kr = 4 * (mj >> 1) + (mj & 1) + 2 * (mj >> 2), ki = kr ^ 2;
#pragma unroll
        for (int h = 0; h < 2; h++) {
            const uint32_t a = zb + (2 * w + h) * 2048;
            stsm_x4(a + ki * 128 + (((4 * c + mi) ^ (ki & 7)) << 4), zi[h][0], zi[h][1], zi[h][2], zi[h][3]);
            stsm_x4(a + kr * 128 + (((4 * c + mi) ^ (kr & 7)) << 4), zr[h][0], zr[h][1], zr[h][2], zr[h][3]);
        }
    }
    TS(15);
    fence_async_smem();
    TS(16);
    named_bar(1 + wg, 128);
    TS(17);
    float acc[16 * NC];
    const uint64_t dz = mkdesc(zb, 4096, 1024, 1);
    wg_fence();
#pragma unroll
    for (int ks = 0; ks < 4; ks++) wgmma_s4(acc, a4[ks], dz + ks * 256, 0x44EEEE44u, ks > 0);
    wg_commit();
    const uint32_t fb = ~lds32(epoch);
    uint32_t mk[NC][3];
#pragma unroll
    for (int c = 0; c < NC; c++) {
        const int k = ((ch0 + c) >> 1) & 3;
        mk[c][2] = !layer && k == 2 * q; mk[c][1] = !layer && k == 2 * q + 1; mk[c][0] = mk[c][2] | layer;
    }
    auto mark = [&](uint32_t v, uint32_t m) { return (v & ~m) | (fb & m); };
    const char* dst[2];
    {
        uint32_t l2;
        asm volatile("mov.u32 %0, %%laneid;" : "=r"(l2));
        const char* base = layer ? (const char*)g_of + (uint32_t)(ch0 / 80) * 327680u + (uint32_t)(ch0 % 80) * 256u : (const char*)g_x2T + (uint32_t)ch0 * (XP * 2u);
#pragma unroll
        for (int h = 0; h < 2; h++) {
            const uint32_t v = (32 * w + l2) ^ (h ? 252u : 0u);
            dst[h] = base + (layer ? (v >> 4) * 20480u + (v & 15u) * 16u : v * 8u);
        }
    }
    wg_wait<0>();
    TS(18);
#pragma unroll
    for (int c = 0; c < NC; c++) {
        uint32_t r[2][4];
#pragma unroll
        for (int j = 0; j < 4; j++) {
            const float* d = acc + 4 * (4 * c + j);
            const uint32_t y0 = pack2(d[0] + d[2], d[1] + d[3]), y1 = pack2(d[0] - d[2], d[1] - d[3]);
            asm("fma.rn.bf16x2 %0, %1, %2, %3;" : "=r"(r[0][j]) : "r"(y0), "r"(oscale[c]), "r"((j & 1) ? x[c][0][j >> 1].y : x[c][0][j >> 1].x));
            asm("fma.rn.bf16x2 %0, %1, %2, %3;" : "=r"(r[1][j]) : "r"(y1), "r"(oscale[c]), "r"((j & 1) ? x[c][1][j >> 1].y : x[c][1][j >> 1].x));
        }
#pragma unroll
        for (int h = 0; h < 2; h++)
            asm volatile("{\n.reg .pred p;\n.reg .b128 t;\n.reg .b64 a, b;\nsetp.ne.u32 p, %5, 0;\nmov.b64 a, {%1, %2};\nmov.b64 b, {%3, %4};\nmov.b128 t, {a, b};\n"
                         "@p st.relaxed.gpu.global.b128 [%0], t;\n@!p st.relaxed.gpu.global.b64 [%6], a;\n@!p st.relaxed.gpu.global.b64 [%6 + 2048], b;\n}"
                         ::"l"(dst[h] + c * 256), "r"(mark(r[h][0], mk[c][0])), "r"(mark(r[h][1], mk[c][1])), "r"(mark(r[h][2], mk[c][2])), "r"(mark(r[h][3], mk[c][1])), "r"(layer), "l"(dst[h] + c * XP * 2) : "memory");
    }
    if (layer == 0 && lane == 0) asm volatile("red.relaxed.gpu.global.add.u32 [%0], %1;" ::"l"(g_xcnt[ch0 >> 6][w]), "n"(NC) : "memory");
    TS(19);
}

#define Q_S0 8
#define R_CONS 192
#define K_CSUN 1
constexpr int K_CSU = K_CSUN;
#define G_MAP 1
constexpr int Q_SP = 4;
#define A_VLO 4
constexpr int Q_ST = 4;
constexpr int Q_AB = 16384, Q_BB = 30720, Q_SB = Q_AB + Q_BB;
constexpr int Q_EROW = 336;
constexpr int Q_ESLOT = 8 * Q_EROW;
constexpr int Q_EOFF = Q_ST * Q_SB;
constexpr int Q_KG = 2 * Q_SB;
static_assert(3 * Q_ESLOT <= 8192 && Q_KG + KG_TABLES <= Q_EOFF + 4096, "exchange slots, kernel generation");
constexpr int F_EO = Q_EOFF, F_S23 = F_EO + 2 * 8192 + 4096, Q_KDUMP = F_S23 + 8192;
constexpr int Q_MISC = Q_KDUMP + 6 * KG_RES;
__host__ __device__ constexpr int w_grp(int j) { return j < 7 ? 2 * Q_SB + 4096 + j * 12800 : 0; }
constexpr int W_RES = Q_AB;
__device__ __forceinline__ int o_slot(int wg, int s) { return W_RES + (((2 * s + 2) & 7) + wg) * 10240; }
__device__ __forceinline__ int w_out(int wg) { return W_RES + (2 + 3 * wg) * 10240; }
static_assert(W_RES + 8 * 10240 == w_grp(0) && w_grp(6) + 12800 <= Q_EOFF && w_grp(3) <= 3 * Q_SB, "phase W layout");

constexpr int Q_WOT = Q_EOFF + 4096;

__device__ unsigned g_epoch;
__device__ __align__(1024) unsigned g_bar[4][16][32];
__device__ __align__(1024) uint4 g_wop[8][80][10][8];
__device__ __align__(1024) uint4 g_csp[8][16][96];
__device__ __align__(1024) uint4 g_stp[16][8][64];
__device__ __align__(1024) uint4 g_sp2[16][8][8][8];
__device__ __align__(1024) uint4 g_halo[128][2][5][32];

struct Bars { uint64_t full[Q_ST], empty[Q_ST], wfull[3], ex[7], res, go, qdone, prep, hdone, idx, fdone0, att[2], wfree, soon[2], fdone1, st[4], kfree, staged, xland[4], ardy[3], spec; };
constexpr int NBAR = sizeof(Bars) / 8;
struct OBars { uint64_t full[8], ready[8], empty[8]; };
struct Misc { float cs[240], mean[2][64], rstd[2][72]; Bars bar[2]; OBars ob; KgShared kg; uint32_t epoch, pad; };
#define MISC(f) (sb + Q_MISC + (uint32_t)offsetof(Misc, f))
constexpr int Q_SMEM = Q_MISC + sizeof(Misc) + TS_SMEM;
__host__ __device__ constexpr int bar_count(int i) {
#define BAR_IS(f) (i == offsetof(Bars, f) / 8)
    return (i >= 4 && i < 8) ? 16 : (BAR_IS(go) || (i >= offsetof(Bars, att) / 8 && i < offsetof(Bars, st) / 8)) ? 4 : (BAR_IS(qdone) || BAR_IS(fdone0)) ? 8 : BAR_IS(prep) ? 96 :
           BAR_IS(hdone) ? 6 : BAR_IS(kfree) ? 24 : BAR_IS(staged) ? 2 : 1;
}
__device__ __forceinline__ void grid_wait(const unsigned* c, int n, unsigned target, int lane) {
    const unsigned* p = c + 32 * min(lane, n - 1);
    unsigned v;
    int spin = 0;
    do { asm volatile("ld.relaxed.gpu.global.u32 %0, [%1];" : "=r"(v) : "l"(p) : "memory"); } while (!__all_sync(~0u, (int)(v - target) >= 0) && ++spin < (1 << 18));
    fence_acquire();
}
__device__ __forceinline__ void grid_arrive(unsigned* c) {
    fence_release();
    asm volatile("red.relaxed.gpu.global.add.u32 [%0], 1;" ::"l"(c) : "memory");
}

#define TMAP(n) ([] { const CUtensorMap* p_; asm volatile("{\n.reg .b64 t;\nmov.b64 t, fused_kernel_param_" #n ";\ncvta.param.u64 %0, t;\n}" : "=l"(p_)); return p_; }())
extern "C" __global__ void __launch_bounds__(384, 1)
fused_kernel(const SsmParams sp, const __grid_constant__ CUtensorMap mX0, const __grid_constant__ CUtensorMap mX1, const __grid_constant__ CUtensorMap mW,
             const __grid_constant__ CUtensorMap mWr,
             const __grid_constant__ CUtensorMap mRes0, const __grid_constant__ CUtensorMap mRes1, const __grid_constant__ CUtensorMap mOut,
             const __grid_constant__ CUtensorMap mWo, const __grid_constant__ CUtensorMap mFin, const __grid_constant__ CUtensorMap mResA) {
    extern __shared__ __align__(1024) char smraw[];
    const uint32_t sb = s2u(smraw);
    int tid, warp, lane, bx, rank, blk, hg, rot, c0;
    int role;
    {
        const int c = blockIdx.x >> 1, d = c - 41, r = d >= 21 ? 3 : d >= 14 ? 2 : d >= 7 ? 1 : 0;
        const int gp = c < 4 ? 0 : c <= 40 ? (c + 7) & 7 : d - 7 * r + 1;
        const int k = c < 4 ? c : c <= 40 ? (c >> 3) + (gp == 0 ? 3 : gp >= 3 && gp < 7 ? 0 : -1) : (gp >= 3 ? 5 : 4) + r;
        role = G_MAP == 1 ? 16 * k + 2 * gp + (blockIdx.x & 1) : G_MAP == 2 ? 16 * gp + 2 * k + (blockIdx.x & 1) : blockIdx.x;
    }
    auto indices = [&] {
        asm volatile("mov.u32 %0, %%tid.x;" : "=r"(tid));
        asm volatile("mov.u32 %0, %1;" : "=r"(bx) : "r"(role));
        warp = __shfl_sync(~0u, tid >> 5, 0); lane = tid & 31;
        rank = bx & 1; blk = bx & 15; hg = bx >> 4;
        const int u = ((blk >> 1) + hg) & 7;
        rot = (5 * u) >> 2; c0 = 16 * (u & 3);
    };
    indices();
    TS_DECL;
    TS_BEGIN;
#define EPOCH lds32(MISC(epoch))
    int layer = 0;
    uint32_t bars = MISC(bar);
#define BAR(f) (bars + (uint32_t)offsetof(Bars, f))
    auto chunk = [&](int it, int s0) {
        const int i = it < s0 ? it : it - 2;
        return (it >> 1) == (s0 >> 1) ? rot + (it & 1) : i < rot ? i : i + 2;
    };
    auto osrc_of = [&](int j) { return j == 0 ? hg : j - 1 < hg ? j - 1 : j; };
    auto issue_w = [&](uint32_t bb, int it, int lay) {
        const int half = rank;
        const int s = it & (Q_ST - 1);
        const uint32_t fb = bb + 8 * s, db = sb + s * Q_SB + Q_AB + half * 15360;
        const int k0 = chunk(it, Q_SP * lay) * 64 + half * 32;
#pragma unroll
        for (int p = 0; p < 3; p++) tma2d_mc(db + p * 4096, TMAP(3), p * DM + hg * 80, k0, fb, 3);
        tma3d_mc(db + 12288, TMAP(4), hg * 80 + 64, k0, 0, fb, 3);
    };
    auto issue_x = [&](int it) {
        const int s = it & (Q_ST - 1), kc = chunk(it, Q_SP * layer);
        mbar_expect(BAR(full) + 8 * s, Q_SB);
        tma3d(sb + s * Q_SB, TMAP(1) + layer, (layer ? blk : kc) * 64, (layer ? kc : blk) * 64, 0, BAR(full) + 8 * s);
    };
    {
        KgParams kp;
        const uint32_t epoch0 = ldg32(sp.epoch);
        kgen_load(kp, bx, warp, lane, sp);
        if (warp < 8) {
            cluster_arrive_relaxed();
        } else {
            if (elect_one()) {
                if (warp < 10) { prefetch_tmap(TMAP(3)); prefetch_tmap(TMAP(4)); } else prefetch_tmap(warp == 10 ? TMAP(1) : TMAP(8));
                const uint32_t b0 = bars + (warp >= 10 ? sizeof(Bars) : 0);
                if (warp & 1) {
#pragma unroll
                    for (int i = 0; i < NBAR / 2; i++) mbar_init(b0 + i * 8, bar_count(i));
                } else {
#pragma unroll
                    for (int i = NBAR / 2; i < NBAR; i++) mbar_init(b0 + i * 8, bar_count(i));
                }
                fence_mbar_init();
            }
            __syncwarp();
            cluster_arrive_relaxed();
            TS(29);
            cluster_wait();
            TS(27);
            if (elect_one()) {
                if (warp < 10) {
                    issue_w(BAR(full), warp - 8, 0);
                } else if (warp == 10) {
                    issue_x(0); issue_x(1);
                    prefetch_l2((const char*)c_fft + bx * (sizeof(c_fft) / 128), sizeof(c_fft) / 128);
                } else {
                    mbar_expect(BAR(idx), 8192 + 6400);
                    asm volatile("cp.async.bulk.tensor.4d.shared::cluster.global.mbarrier::complete_tx::bytes [%0], [%1, {0, 0, %3, %4}], [%2];"
                                 ::"r"(sb + Q_WOT), "l"(TMAP(8)), "r"(BAR(idx)), "r"(10 * hg), "r"(5 * blk) : "memory");
                    bulk_g2s(sb + F_S23, c_fft + 18 * 512, 8192, BAR(idx));
                }
            }
            __syncwarp();
            TS(30);
        }
        indices();
        kgen_tables(kp, sb + Q_KG, sb + Q_KDUMP, MISC(kg), warp, lane, [&] { if (warp < 8) cluster_wait(); } TS_PASS);
        __syncwarp();
        if (lane == 0) { mbar_arrive_cta(BAR(kfree), 0); mbar_arrive_cta(BAR(kfree), 1); }
        if (warp >= 8) {
            const int t2 = tid - 256;
            float csum[10];
            if (warp < 11 && elect_one()) {
#pragma unroll
                for (int i = 0; i < 8; i++) mbar_init(MISC(ob) + (warp - 8) * 64 + i * 8, warp == 10 ? 4 : 1);
                fence_mbar_init();
            }
            __syncwarp();
            if (t2 == 0) sts32(MISC(epoch), epoch0);
            if (t2 < 64) stg128(&g_sp2[blk][hg][0][0] + t2, make_uint4(0, 0, 0, 0));
            if (t2 >= 64 && t2 < 80) stg128(&g_of[hg][blk][640 * ((t2 >> 3) & 1) + 8 * (73 + (t2 & 6)) + 6 + (t2 & 1)], make_uint4(epoch0, epoch0, epoch0, epoch0));
            if (t2 >= 120) stg128((uint4*)g_fs + 8 * bx + t2 - 120, make_uint4(0, 0, 0, 0));
#pragma unroll
            for (int i = 0; i < 2; i++)
                if (t2 + 128 * i < 192) stg128(g_x1T + (uint32_t)cta_channel(bx, 4 * i + 1 + 2 * (t2 >> 6)) * XP + 32 * (t2 & 62) + 48 + 8 * (t2 & 1), make_uint4(0, 0, 0, 0));
#pragma unroll
            for (int i = 0; i < 3; i++)
                if (t2 + 128 * i < 320) stg128(&g_halo[bx][0][0][0] + t2 + 128 * i, make_uint4(0, 0, 0, 0));
            named_bar(13, 128);
            if (warp > 8) {
                const int hw = warp - 9, mi = lane >> 3, mj = lane & 7;
                mbar_wait(BAR(idx), 0);
                if (hw == 2 && elect_one()) { bulk_s2g(&g_wop[hg][5 * blk], sb + Q_WOT, 6400); bulk_commit(); }
                __syncwarp();
                mbar_wait(BAR(full), 0);
                mbar_wait(BAR(full) + 8, 0);
#pragma unroll
                for (int f = 0; f < 10; f++) csum[f] = 0.f;
#pragma unroll K_CSU
                for (int G = 0; G < 5; G++) {
                    const int row = c0 + 40 * rank + 8 * G + mj;
                    const uint32_t b = sb + (row >> 6) * Q_SB + Q_AB + ((row >> 5) & 1) * 15360;
                    uint32_t r[10];
                    ldsm_x4_t(r[0], r[1], r[2], r[3], b + hw * 4096 + (row & 31) * 128 + ((mi ^ mj) << 4));
                    ldsm_x4_t(r[4], r[5], r[6], r[7], b + hw * 4096 + (row & 31) * 128 + (((4 + mi) ^ mj) << 4));
                    ldsm_x2_t(r[8], r[9], b + 12288 + hw * 1024 + (row & 31) * 32 + (((mi & 1) ^ (mj >> 2)) << 4));
#pragma unroll
                    for (int f = 0; f < 10; f++) csum[f] += bf_lo(r[f]) + bf_hi(r[f]);
                }
                const int q = lane & 3;
                float t[3];
#pragma unroll
                for (int j = 0; j < 3; j++) {
                    float v[4];
#pragma unroll
                    for (int k = 0; k < 4; k++) v[k] = 4 * j + k < 10 ? csum[4 * j + k] : 0.f;
                    const float a0 = ((q & 2) ? v[2] : v[0]) + __shfl_xor_sync(~0u, (q & 2) ? v[0] : v[2], 2);
                    const float a1 = ((q & 2) ? v[3] : v[1]) + __shfl_xor_sync(~0u, (q & 2) ? v[1] : v[3], 2);
                    t[j] = ((q & 1) ? a1 : a0) + __shfl_xor_sync(~0u, (q & 1) ? a0 : a1, 1);
                }
                st_ll4(&g_csp[hg][blk][tid - 288], ~EPOCH & 1u, __float_as_uint(t[0]), __float_as_uint(t[1]), __float_as_uint(t[2]));
            }
        }
        TS(1);
    }

    uint4 fa1[4], ftw[4];
    auto conv_tables = [&] {
#pragma unroll
        for (int i = 0; i < 4; i++) { fa1[i] = ldg_tab(i, tid & 127); ftw[i] = ldg_tab(8 + i, tid & 127); }
    };
    if (warp >= 8) {
    asm volatile("setmaxnreg.dec.sync.aligned.u32 %0;" ::"n"(504 - 2 * R_CONS));
    uint32_t ophase = 0;
#pragma unroll 1
    for (; layer < 2; layer++, bars += sizeof(Bars)) {
        indices();
        TS_PHASE(2 * layer);
        if (layer) {
            const int i = warp - 8, g = lane >> 2;
            const uint32_t eb = ~EPOCH, a = sb + i * Q_SB + g * 128 + (((2 * (lane & 3)) ^ g) << 4) + 2 * (g & 6);
            const unsigned* pp = g_xcnt[chunk(i, Q_SP)][(blk < 8 ? blk : 15 - blk) >> 1];
            mbar_wait(BAR(fdone0) - sizeof(Bars), 0);
            if (i == 3) mbar_wait(BAR(fdone1) - sizeof(Bars), 0);
            if (i == 3 && elect_one()) grid_arrive(g_bar[2][hg]);
            __syncwarp();
            uint32_t bad;
            int spin = 0;
            do { asm volatile("ld.relaxed.gpu.global.u32 %0, [%1];" : "=r"(bad) : "l"(pp) : "memory"); } while ((int)(bad + 64 * eb) < 0 && ++spin < (1 << 18));
            fence_async_global();
            TS(1);
            spin = 0;
            do {
                if (elect_one()) {
                    mbar_expect(BAR(xland) + 8 * i, Q_AB);
                    tma3d(sb + i * Q_SB, TMAP(2), blk * 64, chunk(i, Q_SP) * 64, 0, BAR(xland) + 8 * i);
                }
                __syncwarp();
                mbar_wait(BAR(xland) + 8 * i, spin & 1);
                bad = 0;
#pragma unroll
                for (int k = 0; k < 16; k++) bad |= lds32(a + k * 1024) ^ eb;
            } while (__any_sync(~0u, bad & 1u) && ++spin < (1 << 16));
            if (lane == 0) mbar_expect(BAR(full) + 8 * i, Q_BB);
            TS(9);
        }
        if (warp == 8) {
            if (layer) {
                grid_wait(g_bar[2][0], 8, 16 * (EPOCH + 1), lane);
                fence_async_global();
                TS(10);
            }
            if (elect_one()) {
#pragma unroll 1
                for (int it = 2 + 2 * layer; it < 10; it++) {
                    if (it >= Q_ST) mbar_wait(BAR(empty) + 8 * (it & (Q_ST - 1)), ((it >> 2) - 1) & 1);
                    else mbar_wait(BAR(kfree), 0);
                    if (it == Q_ST + Q_SP * layer) mbar_wait(BAR(hdone), 0);
                    issue_x(it);
                    issue_w(BAR(full), it, layer);
                    if (it == Q_SP + 1) mbar_arrive(BAR(spec));
                }
                { prefetch_tmap(TMAP(5) + layer); prefetch_tmap(TMAP(7)); prefetch_tmap(TMAP(10)); }
                if (layer == 0) { mbar_wait(BAR(prep), 0); fence_async_global(); }
#pragma unroll 1
                for (int j = 0; j < 8; j++) {
                    const int b = (j + 1) >> 2;
                    const uint32_t fb = BAR(wfull) + 8 * b;
                    if (j == 0 || j == 3 || j == 7) {
                        mbar_wait(BAR(empty) + 8 * ((2 + b) & 3), b < 2);
                        TS(11 + b);
                        mbar_expect(fb, (b == 0 ? 3 : b == 1 ? 4 : 1) * 12800);
                    }
                    bulk_g2s_mc(sb + w_grp(j) + rank * 6400, &g_wop[hg][osrc_of(j) * 10 + rank * 5], 6400, fb, 3);
                }
                mbar_expect(BAR(res), 20480);
                if (layer) {
                    tma3d(sb + W_RES, TMAP(6), blk * 64, hg * 80, 0, BAR(res));
                } else {
#pragma unroll 1
                    for (int p = 0; p < 2; p++) {
                        tma3d(sb + W_RES + p * 10240, TMAP(10), hg * 80, blk * 64, p, BAR(res));
                        tma3d(sb + W_RES + p * 10240 + 8192, TMAP(5), hg * 80 + 64, blk * 64, p, BAR(res));
                    }
                }
            }
            __syncwarp();
        } else {
            const int ht = tid - 288, hw = warp - 9, mi = lane >> 3, mj = lane & 7, g = lane >> 2, q = lane & 3;
            auto F = [](uint32_t x) { return __uint_as_float(x); };
            auto U = [](float x) { return __float_as_uint(x); };
            const uint32_t lb = layer ^ 1, eb = ~EPOCH & 1u;
            if (layer) mbar_wait(BAR(spec), 0);
            mbar_wait(BAR(full), layer);
            mbar_wait(BAR(full) + 8, layer);
            if (ht == 0) TSX(2, 2);
            uint32_t xf[3][20];
#pragma unroll
            for (int i = 0; i < 3; i++) {
                const int tile = min(hw + 3 * i, 7);
#pragma unroll
                for (int k = 0; k < 5; k++) {
                    const int ch = c0 + 16 * k + 8 * (mi >> 1), tok = 16 * (tile & 3) + 8 * (mi & 1);
                    const uint32_t a = sb + (ch >> 6) * Q_SB + (tile >> 2) * 8192;
                    if (layer == 0) ldsm_x4(xf[i][4 * k], xf[i][4 * k + 1], xf[i][4 * k + 2], xf[i][4 * k + 3], a + (tok + mj) * 128 + ((((ch & 63) >> 3) ^ mj) << 4));
                    else ldsm_x4_t(xf[i][4 * k], xf[i][4 * k + 1], xf[i][4 * k + 2], xf[i][4 * k + 3], a + ((ch & 63) + mj) * 128 + (((tok >> 3) ^ mj) << 4));
                }
            }
            fence_async_smem();
            __syncwarp();
            if (lane == 0) { mbar_arrive_cta(BAR(hdone), 0); mbar_arrive_cta(BAR(hdone), 1); }
            if (ht == 0) TSX(2, 3);
            if (layer == 0) {
                if (hw == 2 && elect_one()) { bulk_wait(); fence_async_global(); grid_arrive(g_bar[3][hg]); }
                __syncwarp();
                mbar_wait(BAR(kfree), 0);
            }
            if (ht == 0) TSX(2, 8);
#pragma unroll 1
            for (int tile = hw; tile < 8; tile += 3) {
                float a[4] = {0.f, 0.f, 0.f, 0.f};
#pragma unroll
                for (int j = 0; j < 20; j++) {
                    const float lo = bf_lo(xf[0][j]), hi = bf_hi(xf[0][j]);
                    a[2 * (j & 1)] += lo + hi; a[2 * (j & 1) + 1] = fmaf(lo, lo, fmaf(hi, hi, a[2 * (j & 1) + 1]));
                    xf[0][j] = xf[1][j]; xf[1][j] = xf[2][j];
                }
#pragma unroll
                for (int j = 0; j < 4; j++) { a[j] += __shfl_xor_sync(~0u, a[j], 1); a[j] += __shfl_xor_sync(~0u, a[j], 2); }
                if (q == 0) st_ll4(&g_stp[blk][hg][8 * tile + g], (U(a[0]) & ~1u) | lb, U(a[1]), U(a[2]), U(a[3]));
            }
            if (ht == 0) TSX(2, 4);
            if (layer == 0) {
                float t[4] = {0.f, 0.f, 0.f, 0.f};
                uint4 v[16];
                int spin = 0;
                uint32_t bad;
                do {
                    bad = 0;
#pragma unroll
                    for (int j = 0; j < 16; j++) v[j] = ld_ll4(&g_csp[hg][j][ht]);
#pragma unroll
                    for (int j = 0; j < 16; j++) bad |= v[j].x ^ eb;
                } while ((bad & 1u) && ++spin < (1 << 18));
#pragma unroll
                for (int j = 0; j < 16; j++) { t[0] += F(v[j].y); t[1] += F(v[j].z); t[2] += F(v[j].w); }
#pragma unroll
                for (int j = 0; j < 3; j++) if (q + 4 * j < 10) sts32(MISC(cs) + 4 * (80 * hw + 20 * (g >> 1) + 2 * (q + 4 * j) + (g & 1)), U(t[j]));
                if (hw == 2) grid_wait(g_bar[3][0], 8, 16 * (EPOCH + 1), lane);
            }
            if (ht == 0) TSX(2, 15);
            if (ht < 80) {
                const bool halo = ht >= 64;
                const int p = halo ? (ht >> 3) & 1 : ht >> 5, i = halo ? (ht & 7) - 8 : 8 + 2 * (ht & 24) + (ht & 7);
                const uint4* src = &g_stp[halo && blk ? blk - 1 : blk][0][halo ? 32 * p + 24 + (ht & 7) : ht];
                uint4 v[8];
                int spin = 0;
                uint32_t bad;
                do {
                    bad = 0;
#pragma unroll
                    for (int j = 0; j < 8; j++) v[j] = ld_ll4(src + 64 * j);
#pragma unroll
                    for (int j = 0; j < 8; j++) bad |= v[j].x ^ lb;
                } while ((bad & 1u) && ++spin < (1 << 18));
                float t[4] = {0.f, 0.f, 0.f, 0.f};
#pragma unroll
                for (int j = 0; j < 8; j++) { t[0] += F(v[j].x); t[1] += F(v[j].y); t[2] += F(v[j].z); t[3] += F(v[j].w); }
                const uint32_t s0 = ln_finish_packed(t[0], t[1]), s1 = ln_finish_packed(t[2], t[3]);
                const uint32_t am = MISC(mean) + 4 * (64 * p + i), ar = MISC(rstd) + 4 * (72 * p + i);
                if (!halo) { sts32(am - 32, U(bf_hi(s0))); sts32(am, U(bf_hi(s1))); sts32(ar, U(frcp(bf_lo(s0)))); }
                sts32(ar + 32, U(frcp(bf_lo(s1))));
            }
            fence_acquire();
            mbar_arrive(BAR(prep));
            if (ht == 0) TSX(2, 5);
        }
        __syncwarp();
        indices();
        {
            const uint4 ko[2] = {ldg_tab(16, tid & 127), ldg_tab(17, tid & 127)};
            conv_tables();
            kernel_stage<1>(ko, sb + Q_KDUMP + 4 * KG_RES, MISC(kg), 4, sb + F_EO + 2 * 8192, warp & 3, lane);
            fence_async_smem();
        }
        {
            const int p = warp & 1;
            const uint32_t fb = EPOCH ^ layer ^ 1, ob = MISC(ob) + 32 * p;
            auto fetch = [&](int j) {
                if (elect_one()) {
                    mbar_expect(ob + 8 * ((j - 1) & 3), 10240);
                    bulk_g2s(sb + o_slot(p, (j - 1) & 3), &g_of[osrc_of(j)][blk][640 * p], 10240, ob + 8 * ((j - 1) & 3));
                }
                __syncwarp();
            };
            if (warp < 10) {
                const uint32_t* pp = &g_of[osrc_of(1 + min(lane >> 2, 6))][blk][640 * p + 8 * (73 + 2 * (lane & 3)) + 7].x;
                mbar_wait(BAR(qdone), 0);
                mbar_wait(BAR(att) + 8 * p, 0);
                uint32_t miss = ~0u;
                int spin = 0;
#pragma unroll 1
                for (int j = 1; j < 8; j++) {
                    while (((miss >> (4 * j - 4)) & 15u) && ++spin < (1 << 18)) {
                        uint32_t v;
                        asm volatile("ld.relaxed.gpu.global.u32 %0, [%1];" : "=r"(v) : "l"(pp) : "memory");
                        miss = __ballot_sync(~0u, (v ^ fb) & 1u);
                        fence_async_global();
                    }
                    if (j == 1) TS(16);
                    if (j > 3) mbar_wait(ob + 128 + 8 * ((j - 1) & 3), layer);
                    fetch(j);
                }
                TS(17);
            } else {
#pragma unroll 1
                for (int j = 1, spin = 0; j < 8;) {
                    const int s = (j - 1) & 3;
                    mbar_wait(ob + 8 * s, (ophase >> s) & 1);
                    ophase ^= 1u << s;
                    const uint32_t a = sb + o_slot(p, s) + (lane >> 2) * 132 + (lane & 3) * 32;
                    uint32_t bad = 0;
#pragma unroll
                    for (int i = 0; i < 10; i++) bad |= lds32(a + i * 1024) ^ fb;
                    if (__any_sync(~0u, bad & 1u) && ++spin < (1 << 16)) { fetch(j); continue; }
                    if (lane == 0) mbar_arrive(ob + 64 + 8 * s);
                    j++;
                }
            }
        }
        TS_PHASE(2 * layer + 1);
        TS(0);
        indices();
        named_bar(3, 128);
        conv_wg<1>(cta_channel(bx, 4), layer, sb + F_EO + 2 * 8192, sb + 2 * Q_SB, sb + F_S23, MISC(kg.kexp) + 16, MISC(epoch), sb, BAR(st), BAR(ardy) + 16, 0,
                   warp, lane, fa1, ftw,
        [&] {
            if (warp == 9) {
                auto F = [](uint32_t x) { return __uint_as_float(x); };
                mbar_wait(BAR(soon) + 8 * (hg >> 2), 0);
                TS(23);
                const uint4* src = &g_sp2[blk][hg][0][0] + lane;
                uint4* dst = (uint4*)(g_fs[(lane >> 2) & 1] + 1024 * (hg >> 2) + 64 * blk + 16 * (hg & 3)) + (lane & 3);
                const bool up = lane & 8;
#pragma unroll 1
                for (int spin = 0; spin < (1 << 18); spin++) {
                    const uint4 a = ld_ll4(src), b = ld_ll4(src + 32);
                    const bool ok = !__any_sync(~0u, ~((a.x ^ layer) & (b.x ^ layer)) & 1u);
                    const float s0 = F(a.x) + F(b.x), q0 = F(a.y) + F(b.y), s1 = F(a.z) + F(b.z), q1 = F(a.w) + F(b.w);
                    float sm = (up ? s1 : s0) + __shfl_xor_sync(~0u, up ? s0 : s1, 8), sq = (up ? q1 : q0) + __shfl_xor_sync(~0u, up ? q0 : q1, 8);
                    sm += __shfl_xor_sync(~0u, sm, 16); sq += __shfl_xor_sync(~0u, sq, 16);
                    const float m = sm * (1.0f / DM), r = frsq(fmaxf(fmaf(sq, 1.0f / DM, fmaf(-m, m, 1e-5f)), 1e-5f));
                    const uint32_t v = __float_as_uint(lane & 16 ? -m * r : r);
                    const uint32_t v0 = __shfl_sync(~0u, v, 4 * lane), v1 = __shfl_sync(~0u, v, 4 * lane + 1), v2 = __shfl_sync(~0u, v, 4 * lane + 2), v3 = __shfl_sync(~0u, v, 4 * lane + 3);
                    if (ok && lane < 8) st_ll4(dst, (v0 & ~1u) | (layer ^ 1), v1, v2, v3);
                    if (ok) break;
                }
            }
            TS(25);
            mbar_wait(BAR(staged), 0);
        }, [&] {
            if (tid == 352) prefetch_tmap(layer ? TMAP(9) : TMAP(2));
        } TS_PASS);
        named_bar(3, 128);
        TS(20);
    }
    } else {
#pragma unroll 1
    for (; layer < 2; layer++, bars += sizeof(Bars)) {
    indices();
    TS_PHASE(2 * layer);
    const int wg = warp >> 2, w = warp & 3;
    const int mi = lane >> 3, mj = lane & 7, g = lane >> 2, q = lane & 3;
    TS(2);
    float acc[120];
#pragma unroll
    for (int i = 0; i < 120; i++) acc[i] = 0.f;
    auto release = [&](int it) {
        if (lane == 0) { mbar_arrive_cta(BAR(empty) + 8 * (it & (Q_ST - 1)), 0); mbar_arrive_cta(BAR(empty) + 8 * (it & (Q_ST - 1)), 1); }
    };
#pragma unroll 1
    for (int it = 0; it < 10; it++) {
        const int s = it & (Q_ST - 1);
        const uint32_t st = sb + s * Q_SB;
        const bool hold = wg == 1 && it == Q_S0;
        if (hold) {
            wg_wait<0>();
            release(it - 1);
            mbar_wait(BAR(go), 0);
        }
        mbar_wait(BAR(full) + 8 * (s), (it >> 2) & 1);
        if (it < 2) TS(3 + it);
        if (it == 6) TS(5);
        if (it == 9) TS(6);
        const uint64_t da = mkdesc(st + wg * 8192, 16, 1024, 1);
        const uint64_t db = mkdesc(st + Q_AB, 4096, 1024, 1);
        const uint64_t dr = mkdesc(st + Q_AB + 12288, 1024, 256, 3);
        if (layer == 0) {
            wg_fence();
#pragma unroll
            for (int ks = 0; ks < 4; ks++) {
                const int sc = 1;
                wgmma_n192<0, 1>(*(float(*)[96]) & acc[0], da + ks * 2, db + (ks >> 1) * 960 + (ks & 1) * 128, sc);
                wgmma_n48<0, 1>(*(float(*)[24]) & acc[96], da + ks * 2, dr + (ks >> 1) * 960 + (ks & 1) * 32, sc);
            }
            wg_commit();
        } else {
            wg_fence();
#pragma unroll
            for (int ks = 0; ks < 4; ks++) {
                const int sc = 1;
                wgmma_n192<1, 1>(*(float(*)[96]) & acc[0], da + ks * 128, db + (ks >> 1) * 960 + (ks & 1) * 128, sc);
                wgmma_n48<1, 1>(*(float(*)[24]) & acc[96], da + ks * 128, dr + (ks >> 1) * 960 + (ks & 1) * 32, sc);
            }
            wg_commit();
        }
        wg_wait<1>();
        if (it > 0 && !hold) release(it - 1);
    }
    if (wg == 0 && lane == 0) mbar_arrive(BAR(go));
    asm volatile("setmaxnreg.inc.sync.aligned.u32 %0;" ::"n"(R_CONS));
    mbar_wait(BAR(prep), 0);
    const uint32_t ob = layer ^ 1;
    const bool first = (blk == 0 && w == 0);
    const bool sel0 = (2 * q > g), sel1 = (2 * q + 1 > g);
    constexpr float SC = 0.22360679774997896f * 1.4426950408889634f;
    const float m0 = __uint_as_float(lds32(MISC(mean) + 4 * (16 * warp + g))), m1 = __uint_as_float(lds32(MISC(mean) + 4 * (16 * warp + g + 8)));
    uint4 cs[3][5];
    auto cs_load = [&](int p) {
#pragma unroll
        for (int i = 0; i < 5; i++) cs[p][i] = lds128(MISC(cs) + 4 * (80 * p + 20 * q + 4 * i));
    };
    cs_load(1); cs_load(2);
    wg_wait<0>();
    TS(7);
    if (lane == 0) mbar_arrive(BAR(qdone));
    uint32_t ql[10], qh[10], kl[10], kh[10], vl[10], vh[10];
    auto fold = [&](int p, int f, int h) {
        const int j = (f < 8) ? 8 * p + f : 24 + 2 * p + (f - 8);
        const float c0 = __uint_as_float(u4(cs[p][f >> 1], 2 * (f & 1))), c1 = __uint_as_float(u4(cs[p][f >> 1], 2 * (f & 1) + 1));
        const float m = h ? m1 : m0;
        return pack2(fmaf(-m, c0, acc[4 * j + 2 * h]), fmaf(-m, c1, acc[4 * j + 2 * h + 1]));
    };
#pragma unroll
    for (int f = 0; f < 10; f++) { vh[f] = fold(2, f, 1); if (f < A_VLO) vl[f] = fold(2, f, 0); }
#pragma unroll
    for (int f = 0; f < 10; f++) kh[f] = fold(1, f, 1);
#pragma unroll
    for (int f = 0; f < A_VLO; f++) asm volatile("" : "+r"(vl[f]));
    {
        const uint32_t mk = w == 3 ? 1u : 0u;
        auto mark = [&](uint32_t& v) { v = (v & ~mk) | (ob & mk); };
        mark(kh[0]); mark(kh[5]); mark(vh[0]); mark(vh[4]); mark(vh[8]);
    }
    if (w == 3) {
        uint4* hp = &g_halo[bx][wg][0][lane];
        st_ll4(hp, kh[0], kh[1], kh[3], kh[4]); st_ll4(hp + 32, kh[5], kh[6], kh[8], kh[9]);
        st_ll4(hp + 64, vh[0], vh[1], vh[2], vh[3]); st_ll4(hp + 96, vh[4], vh[5], vh[6], vh[7]);
        st_ll4(hp + 128, vh[8], vh[9], kh[2], kh[7]);
    } else {
        const uint32_t a = sb + Q_EOFF + wg * 8192 + w * Q_ESLOT + mj * Q_EROW + mi * 16;
        stsm_x4(a, kh[0], kh[1], kh[3], kh[4]);
        stsm_x4(a + 64, kh[5], kh[6], kh[8], kh[9]);
        stsm_x4(a + 128, vh[0], vh[1], vh[2], vh[3]);
        stsm_x4(a + 192, vh[4], vh[5], vh[6], vh[7]);
        stsm_x4(a + 256, vh[8], vh[9], kh[2], kh[7]);
        __syncwarp();
        if (lane == 0) mbar_arrive(BAR(ex) + 8 * warp);
    }
    TS(9);
    cs_load(0);
#pragma unroll
    for (int f = 0; f < 10; f++) { kl[f] = fold(1, f, 0); if (f >= A_VLO) vl[f] = fold(2, f, 0); }
#pragma unroll
    for (int f = 0; f < 10; f++) { ql[f] = fold(0, f, 0); qh[f] = fold(0, f, 1); }
    auto rs = [&](int i) { return __uint_as_float(lds32(MISC(rstd) + 4 * (72 * wg + 16 * w + i))); };
    const float kx0 = rs(2 * q + (sel0 ? 0 : 8)), kx1 = rs(2 * q + (sel1 ? 1 : 9)), ky0 = rs(2 * q + (sel0 ? 8 : 16)), ky1 = rs(2 * q + (sel1 ? 9 : 17));
    const float rx = SC * rs(8 + g), ry = SC * rs(16 + g), cx0 = rx * kx0, cx1 = rx * kx1, cy0 = ry * ky0, cy1 = ry * ky1;
    uint4 hv[5];
    const uint4* hp = &g_halo[bx - 1][wg][0][lane];
    auto prev = [&] {
        if (w > 0) {
            const uint32_t a = sb + Q_EOFF + wg * 8192 + (w - 1) * Q_ESLOT + mj * Q_EROW + mi * 16;
            mbar_wait(BAR(ex) + 8 * (warp - 1), 0);
            ldsm_x4(hv[0].x, hv[0].y, hv[0].z, hv[0].w, a);
            ldsm_x4(hv[1].x, hv[1].y, hv[1].z, hv[1].w, a + 64);
            ldsm_x4_t(hv[2].x, hv[2].y, hv[2].z, hv[2].w, a + 128);
            ldsm_x4_t(hv[3].x, hv[3].y, hv[3].z, hv[3].w, a + 192);
            ldsm_x2_t(hv[4].x, hv[4].y, a + 256);
            ldsm_x2(hv[4].z, hv[4].w, a + 288 - (lane >> 4) * 32);
        } else if (blk > 0) {
#pragma unroll
            for (int f = 0; f < 5; f++) hv[f] = ld_ll4(hp + 32 * f);
        } else {
#pragma unroll
            for (int f = 0; f < 5; f++) hv[f] = make_uint4(0, 0, 0, 0);
        }
    };
    uint32_t vt[10][2];
#pragma unroll
    for (int f = 0; f < 10; f++) { vt[f][0] = movm_t(vl[f]); vt[f][1] = movm_t(vh[f]); }
    prev();
    TS(10);
    auto FA = [](int h) { return h == 0 ? 0 : h == 1 ? 3 : h == 2 ? 5 : 8; };
    auto FH = [](int h) { return h < 2 ? 2 : 7; };
    const uint32_t pm = (sel0 ? 0xFFFFu : 0u) | (sel1 ? 0xFFFF0000u : 0u);
    auto softmax = [&](float x0, float x1, float k0, float k1) {
        float mx = fmaxf(x0, x1);
        mx = fmaxf(mx, __shfl_xor_sync(~0u, mx, 1));
        mx = fmaxf(mx, __shfl_xor_sync(~0u, mx, 2));
        x0 = ex2(x0 - mx); x1 = ex2(x1 - mx);
        float sx = x0 + x1;
        sx += __shfl_xor_sync(~0u, sx, 1);
        sx += __shfl_xor_sync(~0u, sx, 2);
        const float ix = frcp(sx);
        return pack2(x0 * k0 * ix, x1 * k1 * ix);
    };
    uint32_t qm[4][2], py[4];
    float sl[4][2];
#pragma unroll
    for (int h = 0; h < 4; h++) {
        const int fa = FA(h), fb = fa + 1, fh = FH(h);
        const bool mine = (h & 1) ? (q >= 2) : (q < 2);
        qm[h][0] = mine ? ql[fh] : 0u; qm[h][1] = mine ? qh[fh] : 0u;
        float S1[4] = {0.f, 0.f, 0.f, 0.f}, S2[4] = {0.f, 0.f, 0.f, 0.f};
        mma16816(S1, ql[fa], qh[fa], ql[fb], qh[fb], kl[fa], kl[fb]); mma1688(S1, qm[h][0], qm[h][1], kl[fh]);
        mma16816(S2, ql[fa], qh[fa], ql[fb], qh[fb], kh[fa], kh[fb]); mma1688(S2, qm[h][0], qm[h][1], kh[fh]);
        sl[h][0] = S1[0]; sl[h][1] = S1[1];
        py[h] = softmax((sel0 ? S1[2] : S2[2]) * cy0, (sel1 ? S1[3] : S2[3]) * cy1, ky0, ky1);
    }
    TS(11);
    if (w == 0 && blk > 0) {
        ll_check5(hv, hp, ob);
#pragma unroll
        for (int f = 2; f < 4; f++) hv[f] = make_uint4(movm_t(hv[f].x), movm_t(hv[f].y), movm_t(hv[f].z), movm_t(hv[f].w));
        hv[4].x = movm_t(hv[4].x); hv[4].y = movm_t(hv[4].y);
    }
    const uint32_t kp[10] = {hv[0].x, hv[0].y, hv[4].z, hv[0].z, hv[0].w, hv[1].x, hv[1].y, hv[4].w, hv[1].z, hv[1].w};
    const uint32_t vp[10] = {hv[2].x, hv[2].y, hv[2].z, hv[2].w, hv[3].x, hv[3].y, hv[3].z, hv[3].w, hv[4].x, hv[4].y};
    TS(12);
    const uint4 ko[2] = {ldg_tab(16, tid & 127), ldg_tab(17, tid & 127)};
    const float bx0 = first && sel0 ? -INFINITY : 0.f, bx1 = first && sel1 ? -INFINITY : 0.f;
    float oacc[10][4];
#pragma unroll
    for (int h = 0; h < 4; h++) {
        const int fa = FA(h), fb = fa + 1, fh = FH(h);
        const bool mine = (h & 1) ? (q >= 2) : (q < 2);
        float S0[4] = {0.f, 0.f, 0.f, 0.f};
        mma16816(S0, ql[fa], qh[fa], ql[fb], qh[fb], kp[fa], kp[fb]); mma1688(S0, qm[h][0], qm[h][1], kp[fh]);
        const uint32_t px = softmax(fmaf(sel0 ? S0[0] : sl[h][0], cx0, bx0), fmaf(sel1 ? S0[1] : sl[h][1], cx1, bx1), kx0, kx1);
#pragma unroll
        for (int i = 0; i < 3; i++) {
            const int f = (i == 0) ? fa : (i == 1) ? fb : fh;
            float O[4] = {0.f, 0.f, 0.f, 0.f};
            mma16816(O, px & ~pm, py[h] & pm, 0u, py[h] & ~pm, vt[f][0], vt[f][1]);
            mma1688(O, px & pm, 0u, vp[f]);
            if (i < 2 || !(h & 1) || mine) { oacc[f][0] = O[0]; oacc[f][1] = O[1]; oacc[f][2] = O[2]; oacc[f][3] = O[3]; }
        }
    }
    TS(13);
    float aw[40];
    uint4 of[5];
    {
        const uint32_t fb = EPOCH ^ ob, mk[2] = {q == 0 || mj == 2 * w, q == 0 || mj == 2 * w + 1};
        uint32_t* dst = &g_of[hg][blk][640 * wg + 16 * w].x + lane;
#pragma unroll
        for (int i = 0; i < 20; i++) {
            const uint32_t v = (pack2(oacc[i >> 1][2 * (i & 1)], oacc[i >> 1][2 * (i & 1) + 1]) & ~mk[i & 1]) | (fb & mk[i & 1]);
            u4r(of[i >> 2], i & 3) = v;
            asm volatile("st.relaxed.gpu.global.u32 [%0], %1;" ::"l"(dst + 256 * (i >> 1) + 32 * (i & 1)), "r"(v) : "memory");
        }
        if (lane == 0) mbar_arrive(BAR(att) + 8 * wg);
        TS(14);
    }
    const uint32_t obar = MISC(ob) + 32 * wg;
    named_bar(1 + wg, 128);
    kernel_stage<2>(ko, sb + Q_KDUMP + 2 * wg * KG_RES, MISC(kg), 2 * wg, sb + F_EO + wg * 8192, w, lane);
    TS(15);
    uint32_t res[20];
    mbar_wait(BAR(res), 0);
    const uint32_t ta = (8 * (mi >> 1) + mj) * 128 + (((2 * w + (mi & 1)) ^ mj) << 4);
    if (layer == 0) {
        const int tok = 16 * w + 8 * (mi & 1) + mj;
#pragma unroll
        for (int k = 0; k < 4; k++)
            ldsm_x4(res[4 * k], res[4 * k + 1], res[4 * k + 2], res[4 * k + 3], sb + W_RES + wg * 10240 + tok * 128 + (((2 * k + (mi >> 1)) ^ mj) << 4));
        ldsm_x4(res[16], res[17], res[18], res[19], sb + W_RES + wg * 10240 + 8192 + tok * 32 + (((mi >> 1) ^ (mj >> 2)) << 4));
    } else {
#pragma unroll
        for (int k = 0; k < 5; k++) ldsm_x4_t(res[4 * k], res[4 * k + 1], res[4 * k + 2], res[4 * k + 3], sb + W_RES + wg * 10240 + k * 2048 + ta);
    }
    fence_async_smem();
    __syncwarp();
    if (lane == 0) mbar_arrive(obar + 128 + 24);
    {
#pragma unroll
        for (int i = 0; i < 20; i++) { aw[2 * i] = bf_lo(res[i]); aw[2 * i + 1] = bf_hi(res[i]); }
        mbar_wait(BAR(wfull), 0);
        const uint64_t dm = mkdesc(sb + w_grp(0), 1280, 128, 0);
        wg_fence();
#pragma unroll
        for (int k = 0; k < 5; k++) wgmma_rs80(aw, of[k], dm + k * 160, 1);
        wg_commit();
    }
    conv_tables();
    wg_wait<0>();
    TS(8);
#pragma unroll 1
    for (int j = 1; j < 8; j++) {
        const int s = (j - 1) & 3;
        const uint64_t da = mkdesc(sb + o_slot(wg, s), 1024, 128, 0), dm = mkdesc(sb + w_grp(j), 1280, 128, 0);
        if (s == 2) mbar_wait(BAR(wfull) + 2 * (j + 1), 0);
        mbar_wait(obar + 64 + 8 * s, s == 3 ? layer : j > 4);
        if (j == 1) TS(17);
        if (j == 5) TS(18);
        wg_fence();
#pragma unroll
        for (int k = 0; k < 5; k++) wgmma_ss80(aw, da + k * 128, dm + k * 160);
        wg_commit();
        wg_wait<1>();
        if (j > 1 && j < 5 && lane == 0) mbar_arrive(obar + 128 + 8 * (j - 2));
    }
    if (lane == 0) mbar_arrive(BAR(soon) + 8 * wg);
    named_bar(1 + wg, 128);
    wg_wait<0>();
    TS(19);
    {
        float a[2][4] = {{0.f, 0.f, 0.f, 0.f}, {0.f, 0.f, 0.f, 0.f}};
#pragma unroll
        for (int i = 0; i < 40; i++) { a[i & 1][i & 2] += aw[i]; a[i & 1][(i & 2) + 1] = fmaf(aw[i], aw[i], a[i & 1][(i & 2) + 1]); }
#pragma unroll
        for (int j = 0; j < 4; j++) { a[0][j] += a[1][j]; a[0][j] += __shfl_xor_sync(~0u, a[0][j], 1); a[0][j] += __shfl_xor_sync(~0u, a[0][j], 2); }
        if (q == 0) st_ll4(&g_sp2[blk][warp][hg][g], (__float_as_uint(a[0][0]) & ~1u) | ob, __float_as_uint(a[0][1]), __float_as_uint(a[0][2]), __float_as_uint(a[0][3]));
    }
    TS(23);
#pragma unroll
    for (int i = 0; i < 20; i++) res[i] = pack2(aw[2 * i], aw[2 * i + 1]);
    {
        const uint32_t mk = (g & 3) ? 0u : 0x00010001u;
#pragma unroll
        for (int k = 0; k < 5; k++) {
            uint32_t m[4];
#pragma unroll
            for (int i = 0; i < 4; i++) m[i] = (res[4 * k + i] & ~mk) | (mk & (0u - ob));
            stsm_x4_t(sb + w_out(wg) + k * 2048 + ta, m[0], m[1], m[2], m[3]);
        }
        fence_async_smem();
        named_bar(1 + wg, 128);
        if (w == 0 && elect_one()) {
            asm volatile("cp.async.bulk.tensor.2d.global.shared::cta.bulk_group [%0, {%2, %3}], [%1];"
                         ::"l"(TMAP(7)), "r"(sb + w_out(wg)), "r"(1024 * wg + 64 * blk), "r"(hg * 80) : "memory");
            bulk_commit();
            mbar_arrive(BAR(staged));
        }
        __syncwarp();
        TS(20);
    }
    if (layer) {
#pragma unroll
        for (int k = 0; k < 5; k++) stsm_x4_t(sb + W_RES + wg * 10240 + k * 2048 + ta, res[4 * k], res[4 * k + 1], res[4 * k + 2], res[4 * k + 3]);
    }
    TS(22);
    TS_PHASE(2 * layer + 1);
    TS(0);
    indices();
    conv_wg<2>(cta_channel(bx, 2 * (warp >> 2)), layer, sb + F_EO + (warp >> 2) * 8192, sb + (1 + 2 * (warp >> 2)) * Q_SB, sb + F_S23, MISC(kg.kexp) + 8 * (warp >> 2),
               MISC(epoch), sb, BAR(st), BAR(ardy) + 8 * (warp >> 2), BAR(fdone0), warp, lane, fa1, ftw, [&] {
        if ((warp & 3) == 0 && elect_one()) {
            asm volatile("cp.async.bulk.wait_group.read 0;" ::: "memory");
            if (layer == 0) { mbar_arrive_cta(BAR(wfree), 0); mbar_arrive_cta(BAR(wfree), 1); }
        }
        __syncwarp();
        if (warp == 0) mbar_wait(BAR(staged), 0);
    }, [&] {
        if (layer == 0 && warp >= 4 && elect_one()) { mbar_wait(BAR(wfree), 0); issue_w(BAR(full) + sizeof(Bars), warp - 4, 1); }
        __syncwarp();
    } TS_PASS);
    __syncwarp();
    if (lane == 0) mbar_arrive(warp < 4 ? BAR(fdone0) : BAR(fdone1));
    TS(20);
    asm volatile("setmaxnreg.dec.sync.aligned.u32 168;");
    }
    named_bar(1 + (warp >> 2), 128);
    asm volatile("setmaxnreg.dec.sync.aligned.u32 %0;" ::"n"(504 - 2 * R_CONS));
    }
    indices();
    const int cq = 4 * (warp >> 1) + (lane & 3), tg = 8 * (warp & 1) + (lane >> 2);
    const uint32_t fb = ~EPOCH & 1u;
    uint2 xr[4][2];
    __syncthreads();
    if (tid < 320) {
#pragma unroll
        for (int i = 0; i < 8; i++) {
            const int ch = 4 * cq + (i >> 1);
            asm volatile("ld.shared.v2.u32 {%0, %1}, [%2];" : "=r"(xr[i >> 1][i & 1].x), "=r"(xr[i >> 1][i & 1].y)
                         : "r"(sb + W_RES + (i & 1) * 10240 + ch * 128 + (((tg >> 1) ^ (ch & 7)) << 4) + (tg & 1) * 8) : "memory");
        }
    }
    if (tid < 320) {
        const uint4* src = &g_of[hg][blk][64 * cq + tg];
        uint4 v[4];
#pragma unroll
        for (int i = 0; i < 4; i++) v[i] = make_uint4(~fb, 0, 0, 0);
        int spin = 0;
        while (true) {
#pragma unroll
            for (int i = 0; i < 4; i++) if ((v[i].x ^ fb) & 1u) v[i] = ld_ll4(src + 16 * i);
            if (!(((v[0].x ^ fb) | (v[1].x ^ fb) | (v[2].x ^ fb) | (v[3].x ^ fb)) & 1u) || ++spin >= (1 << 18)) break;
        }
        TS(21);
#pragma unroll
        for (int i = 0; i < 16; i++) asm("add.rn.bf16x2 %0, %0, %1;" : "+r"(u4r(v[i >> 2], i & 3)) : "r"((i & 1) ? xr[i >> 2][(i >> 1) & 1].y : xr[i >> 2][(i >> 1) & 1].x));
#pragma unroll
        for (int j = 0; j < 8; j++) {
            const uint32_t sel = (j & 2) ? 0x7632 : 0x5410;
            const int k = 2 * (j & 1) + (j >> 2);
            asm volatile("st.shared.v2.u32 [%0], {%1, %2};" ::"r"(sb + 2 * Q_SB + (16 * j + tg) * 160 + cq * 8),
                         "r"(__byte_perm(u4(v[0], k), u4(v[1], k), sel)), "r"(__byte_perm(u4(v[2], k), u4(v[3], k), sel)) : "memory");
        }
        fence_async_smem();
    }
    __syncthreads();
    if (warp == 0 && elect_one()) {
        asm volatile("cp.async.bulk.tensor.3d.global.shared::cta.bulk_group [%0, {%2, %3, 0}], [%1];" ::"l"(TMAP(9)), "r"(sb + 2 * Q_SB), "r"(80 * hg), "r"(16 * blk) : "memory");
        bulk_commit();
        asm volatile("cp.async.bulk.wait_group.read 0;" ::: "memory");
    }
    if (bx == 0 && tid == 0) g_epoch = (EPOCH + 1) & 0x3FFFFFFFu;
    TS(22);
    TS_END;
}
typedef CUresult (*EncodeTiledFn)(CUtensorMap*, CUtensorMapDataType, cuuint32_t, void*, const cuuint64_t*, const cuuint64_t*, const cuuint32_t*,
                                  const cuuint32_t*, CUtensorMapInterleave, CUtensorMapSwizzle, CUtensorMapL2promotion, CUtensorMapFloatOOBfill);

static void make_map(EncodeTiledFn enc, CUtensorMap* m, const void* base, int rank, const cuuint64_t* dims, const cuuint64_t* strides,
                     const cuuint32_t* box, CUtensorMapSwizzle sw) {
    cuuint32_t es[4] = {1, 1, 1, 1};
    enc(m, CU_TENSOR_MAP_DATA_TYPE_BFLOAT16, rank, (void*)base, dims, strides, box, es, CU_TENSOR_MAP_INTERLEAVE_NONE, sw,
        sw == CU_TENSOR_MAP_SWIZZLE_128B ? CU_TENSOR_MAP_L2_PROMOTION_L2_128B : CU_TENSOR_MAP_L2_PROMOTION_NONE, CU_TENSOR_MAP_FLOAT_OOB_FILL_NONE);
}

template <typename... KArgs, typename... Args>
static void launch(void (*kern)(KArgs...), int grid, int block, int smem, int cluster, bool pdl, Args... args) {
    cudaLaunchConfig_t cfg = {};
    cfg.gridDim = dim3(grid); cfg.blockDim = dim3(block); cfg.dynamicSmemBytes = smem; cfg.stream = cudaStreamPerThread;
    cudaLaunchAttribute at[2];
    int n = 0;
    if (cluster > 1) { at[n].id = cudaLaunchAttributeClusterDimension; at[n].val.clusterDim.x = cluster; at[n].val.clusterDim.y = 1; at[n].val.clusterDim.z = 1; n++; }
    if (pdl) { at[n].id = cudaLaunchAttributeProgrammaticStreamSerialization; at[n].val.programmaticStreamSerializationAllowed = 1; n++; }
    cfg.attrs = at; cfg.numAttrs = n;
    cudaLaunchKernelEx(&cfg, kern, KArgs(args)...);
}

struct HostState {
    bool ready = false;
    const void* key[4] = {nullptr, nullptr, nullptr, nullptr};
    CUtensorMap mX[2], mRes[2], mW, mWr, mWo, mOut, mFin, mResA;
    bf16 *x1T, *x2T;
    unsigned* epoch;
};

extern "C" void kernel_launch(void* const* d_in, const int* in_sizes, int n_in, void* d_out, int out_size) {
    const bf16* x = (const bf16*)d_in[0];
    const bf16* wqkv = (const bf16*)d_in[1];
    const bf16* wo = (const bf16*)d_in[2];
    const bf16* lar = (const bf16*)d_in[4];
    const bf16* aim = (const bf16*)d_in[5];
    const bf16* cre = (const bf16*)d_in[6];
    const bf16* cim = (const bf16*)d_in[7];
    const bf16* logdt = (const bf16*)d_in[8];
    const bf16* dskip = (const bf16*)d_in[9];
    static HostState hs;
    if (!hs.ready || hs.key[0] != wqkv || hs.key[1] != wo || hs.key[2] != x || hs.key[3] != d_out) {
        void* fn = nullptr;
        cudaDriverEntryPointQueryResult qr;
        cudaGetDriverEntryPoint("cuTensorMapEncodeTiled", &fn, cudaEnableDefault, &qr);
        EncodeTiledFn enc = (EncodeTiledFn)fn;
        cudaGetSymbolAddress((void**)&hs.epoch, g_epoch);
        cudaGetSymbolAddress((void**)&hs.x1T, g_x1T);
        cudaGetSymbolAddress((void**)&hs.x2T, g_x2T);
        {
            cuuint64_t d[3] = {DM, SEQ / 2, 2}, s[2] = {DM * 4, DM * 2};
            cuuint32_t b[3] = {64, 64, 2}, ba[3] = {64, 64, 1}, br[3] = {16, 64, 1};
            make_map(enc, &hs.mX[0], x, 3, d, s, b, CU_TENSOR_MAP_SWIZZLE_128B);
            make_map(enc, &hs.mResA, x, 3, d, s, ba, CU_TENSOR_MAP_SWIZZLE_128B);
            make_map(enc, &hs.mRes[0], x, 3, d, s, br, CU_TENSOR_MAP_SWIZZLE_32B);
            cuuint64_t d2[3] = {SEQ / 2, DM, 2}, s2[2] = {XP * 2, SEQ};
            cuuint32_t b2[3] = {64, 80, 2};
            make_map(enc, &hs.mX[1], hs.x2T, 3, d2, s2, b, CU_TENSOR_MAP_SWIZZLE_128B);
            make_map(enc, &hs.mRes[1], hs.x2T, 3, d2, s2, b2, CU_TENSOR_MAP_SWIZZLE_128B);
            cuuint64_t d3[2] = {SEQ, DM};
            make_map(enc, &hs.mOut, hs.x1T, 2, d3, s2, b2, CU_TENSOR_MAP_SWIZZLE_128B);
        }
        { cuuint64_t d[2] = {3 * DM, DM}, s[1] = {3 * DM * 2}; cuuint32_t b[2] = {64, 32};
          make_map(enc, &hs.mW, wqkv, 2, d, s, b, CU_TENSOR_MAP_SWIZZLE_128B); }
        { cuuint64_t d[3] = {DM, DM, 3}, s[2] = {3 * DM * 2, DM * 2}; cuuint32_t b[3] = {16, 32, 3};
          make_map(enc, &hs.mWr, wqkv, 3, d, s, b, CU_TENSOR_MAP_SWIZZLE_32B); }
        { cuuint64_t d[4] = {8, 8, DM / 8, DM / 8}, s[3] = {DM * 2, 16, DM * 16}; cuuint32_t b[4] = {8, 8, 10, 5};
          make_map(enc, &hs.mWo, wo, 4, d, s, b, CU_TENSOR_MAP_SWIZZLE_NONE); }
        { cuuint64_t d[3] = {DM, SEQ / 8, 8}, s[2] = {DM * 16, DM * 2}; cuuint32_t b[3] = {80, 16, 8};
          make_map(enc, &hs.mFin, d_out, 3, d, s, b, CU_TENSOR_MAP_SWIZZLE_NONE); }
        cudaFuncSetAttribute(fused_kernel, cudaFuncAttributeMaxDynamicSharedMemorySize, Q_SMEM);
        hs.key[0] = wqkv; hs.key[1] = wo; hs.key[2] = x; hs.key[3] = d_out;
        hs.ready = true;
    }
    const SsmParams sp = {lar, aim, cre, cim, logdt, dskip, hs.epoch};
    launch(fused_kernel, 128, 384, Q_SMEM, 2, false, sp, hs.mX[0], hs.mX[1], hs.mW, hs.mWr, hs.mRes[0], hs.mRes[1], hs.mOut, hs.mWo, hs.mFin, hs.mResA);
}
```

```cpp
#include <cuda_runtime.h>
#include <cuda.h>
#include <cuda_bf16.h>
#include <cuda_fp16.h>
#include <stdint.h>

typedef __nv_bfloat16 bf16;

constexpr int SEQ = 2048;
constexpr int DM  = 640;
constexpr int XP  = SEQ + 64;
constexpr int NMODE = 192;

__device__ __forceinline__ uint32_t s2u(const void* p) { return (uint32_t)__cvta_generic_to_shared(p); }
__device__ __forceinline__ void mbar_init(uint32_t b, int c) { asm volatile("mbarrier.init.shared::cta.b64 [%0], %1;" ::"r"(b), "r"(c)); }
__device__ __forceinline__ void mbar_expect(uint32_t b, uint32_t bytes) { asm volatile("mbarrier.arrive.expect_tx.shared::cta.b64 _, [%0], %1;" ::"r"(b), "r"(bytes) : "memory"); }
__device__ __forceinline__ void mbar_arrive(uint32_t b) { asm volatile("mbarrier.arrive.shared::cta.b64 _, [%0];" ::"r"(b) : "memory"); }
__device__ __forceinline__ void mbar_arrive_cta(uint32_t b, uint32_t cta) {
    asm volatile("{\n.reg .b32 ra;\nmapa.shared::cluster.u32 ra, %0, %1;\nmbarrier.arrive.shared::cluster.b64 _, [ra];\n}" ::"r"(b), "r"(cta) : "memory");
}
__device__ __forceinline__ void mbar_wait(uint32_t b, uint32_t ph) {
#ifdef M_SAFE
    asm volatile("{\n.reg .pred p;\n.reg .u32 n;\nmbarrier.try_wait.parity.shared::cta.b64 p, [%0], %1;\n@p bra D;\nmov.u32 n, 0;\n"
                 "W: mbarrier.try_wait.parity.shared::cta.b64 p, [%0], %1;\n@p bra D;\nadd.u32 n, n, 1;\nsetp.lt.u32 p, n, 4194304;\n@p bra W;\ntrap;\nD:\n}"
                 ::"r"(b), "r"(ph) : "memory");
#else
    asm volatile("{\n.reg .pred p;\nW: mbarrier.try_wait.parity.shared::cta.b64 p, [%0], %1;\n@!p bra W;\n}" ::"r"(b), "r"(ph) : "memory");
#endif
}
__device__ __forceinline__ void fence_mbar_init() { asm volatile("fence.mbarrier_init.release.cluster;" ::: "memory"); }
__device__ __forceinline__ void cluster_sync() { asm volatile("barrier.cluster.arrive.aligned;\nbarrier.cluster.wait.aligned;" ::: "memory"); }
__device__ __forceinline__ void pdl_wait() { asm volatile("griddepcontrol.wait;" ::: "memory"); }
__device__ __forceinline__ void pdl_launch() { asm volatile("griddepcontrol.launch_dependents;" ::: "memory"); }
__device__ __forceinline__ void named_bar(int id, int n) { asm volatile("bar.sync %0, %1;" ::"r"(id), "r"(n) : "memory"); }
__device__ __forceinline__ void fence_async_smem() { asm volatile("fence.proxy.async.shared::cta;" ::: "memory"); }

__device__ __forceinline__ void tma2d(uint32_t dst, const CUtensorMap* m, int c0, int c1, uint32_t bar) {
    asm volatile("cp.async.bulk.tensor.2d.shared::cluster.global.mbarrier::complete_tx::bytes [%0], [%1, {%3, %4}], [%2];"
                 ::"r"(dst), "l"(m), "r"(bar), "r"(c0), "r"(c1) : "memory");
}
__device__ __forceinline__ void tma2d_mc(uint32_t dst, const CUtensorMap* m, int c0, int c1, uint32_t bar, uint16_t mask) {
    asm volatile("cp.async.bulk.tensor.2d.shared::cluster.global.mbarrier::complete_tx::bytes.multicast::cluster [%0], [%1, {%3, %4}], [%2], %5;"
                 ::"r"(dst), "l"(m), "r"(bar), "r"(c0), "r"(c1), "h"(mask) : "memory");
}
__device__ __forceinline__ void tma3d(uint32_t dst, const CUtensorMap* m, int c0, int c1, int c2, uint32_t bar) {
    asm volatile("cp.async.bulk.tensor.3d.shared::cluster.global.mbarrier::complete_tx::bytes [%0], [%1, {%3, %4, %5}], [%2];"
                 ::"r"(dst), "l"(m), "r"(bar), "r"(c0), "r"(c1), "r"(c2) : "memory");
}
__device__ __forceinline__ void tma3d_mc(uint32_t dst, const CUtensorMap* m, int c0, int c1, int c2, uint32_t bar, uint16_t mask) {
    asm volatile("cp.async.bulk.tensor.3d.shared::cluster.global.mbarrier::complete_tx::bytes.multicast::cluster [%0], [%1, {%3, %4, %5}], [%2], %6;"
                 ::"r"(dst), "l"(m), "r"(bar), "r"(c0), "r"(c1), "r"(c2), "h"(mask) : "memory");
}
__device__ __forceinline__ void bulk_g2s(uint32_t dst, const void* src, uint32_t bytes, uint32_t bar) {
    asm volatile("cp.async.bulk.shared::cluster.global.mbarrier::complete_tx::bytes [%0], [%1], %2, [%3];"
                 ::"r"(dst), "l"(src), "r"(bytes), "r"(bar) : "memory");
}
__device__ __forceinline__ void bulk_g2s_mc(uint32_t dst, const void* src, uint32_t bytes, uint32_t bar, uint16_t mask) {
    asm volatile("cp.async.bulk.shared::cluster.global.mbarrier::complete_tx::bytes.multicast::cluster [%0], [%1], %2, [%3], %4;"
                 ::"r"(dst), "l"(src), "r"(bytes), "r"(bar), "h"(mask) : "memory");
}
__device__ __forceinline__ void prefetch_l2(const void* p, uint32_t bytes) { asm volatile("cp.async.bulk.prefetch.L2.global [%0], %1;" ::"l"(p), "r"(bytes) : "memory"); }
__device__ __forceinline__ void prefetch_tmap(const CUtensorMap* m) { asm volatile("prefetch.tensormap [%0];" ::"l"(m) : "memory"); }

__device__ __forceinline__ void wg_fence() { asm volatile("wgmma.fence.sync.aligned;" ::: "memory"); }
__device__ __forceinline__ void wg_commit() { asm volatile("wgmma.commit_group.sync.aligned;" ::: "memory"); }
template <int N> __device__ __forceinline__ void wg_wait() { asm volatile("wgmma.wait_group.sync.aligned %0;" ::"n"(N) : "memory"); }
__device__ __forceinline__ uint64_t mkdesc(uint32_t addr, uint32_t lbo, uint32_t sbo, uint32_t mode) {
    return (uint64_t)((addr & 0x3FFFF) >> 4) | ((uint64_t)(lbo >> 4) << 16) | ((uint64_t)(sbo >> 4) << 32) | ((uint64_t)mode << 62);
}

__device__ __forceinline__ void mma16816(float (&c)[4], uint32_t a0, uint32_t a1, uint32_t a2, uint32_t a3, uint32_t b0, uint32_t b1) {
    asm("mma.sync.aligned.m16n8k16.row.col.f32.bf16.bf16.f32 {%0,%1,%2,%3},{%4,%5,%6,%7},{%8,%9},{%0,%1,%2,%3};"
                 : "+f"(c[0]), "+f"(c[1]), "+f"(c[2]), "+f"(c[3]) : "r"(a0), "r"(a1), "r"(a2), "r"(a3), "r"(b0), "r"(b1));
}
__device__ __forceinline__ void mma1688(float (&c)[4], uint32_t a0, uint32_t a1, uint32_t b0) {
    asm("mma.sync.aligned.m16n8k8.row.col.f32.bf16.bf16.f32 {%0,%1,%2,%3},{%4,%5},{%6},{%0,%1,%2,%3};"
                 : "+f"(c[0]), "+f"(c[1]), "+f"(c[2]), "+f"(c[3]) : "r"(a0), "r"(a1), "r"(b0));
}
__device__ __forceinline__ void ldsm_x4(uint32_t& r0, uint32_t& r1, uint32_t& r2, uint32_t& r3, uint32_t a) {
    asm volatile("ldmatrix.sync.aligned.m8n8.x4.shared.b16 {%0,%1,%2,%3}, [%4];" : "=r"(r0), "=r"(r1), "=r"(r2), "=r"(r3) : "r"(a) : "memory");
}
__device__ __forceinline__ void ldsm_x4_t(uint32_t& r0, uint32_t& r1, uint32_t& r2, uint32_t& r3, uint32_t a) {
    asm volatile("ldmatrix.sync.aligned.m8n8.x4.trans.shared.b16 {%0,%1,%2,%3}, [%4];" : "=r"(r0), "=r"(r1), "=r"(r2), "=r"(r3) : "r"(a) : "memory");
}
__device__ __forceinline__ void ldsm_x2(uint32_t& r0, uint32_t& r1, uint32_t a) {
    asm volatile("ldmatrix.sync.aligned.m8n8.x2.shared.b16 {%0,%1}, [%2];" : "=r"(r0), "=r"(r1) : "r"(a) : "memory");
}
__device__ __forceinline__ void ldsm_x2_t(uint32_t& r0, uint32_t& r1, uint32_t a) {
    asm volatile("ldmatrix.sync.aligned.m8n8.x2.trans.shared.b16 {%0,%1}, [%2];" : "=r"(r0), "=r"(r1) : "r"(a) : "memory");
}
__device__ __forceinline__ void stsm_x4(uint32_t a, uint32_t r0, uint32_t r1, uint32_t r2, uint32_t r3) {
    asm volatile("stmatrix.sync.aligned.m8n8.x4.shared.b16 [%0], {%1,%2,%3,%4};" ::"r"(a), "r"(r0), "r"(r1), "r"(r2), "r"(r3) : "memory");
}
__device__ __forceinline__ void stsm_x4_t(uint32_t a, uint32_t r0, uint32_t r1, uint32_t r2, uint32_t r3) {
    asm volatile("stmatrix.sync.aligned.m8n8.x4.trans.shared.b16 [%0], {%1,%2,%3,%4};" ::"r"(a), "r"(r0), "r"(r1), "r"(r2), "r"(r3) : "memory");
}
__device__ __forceinline__ void stsm_x2(uint32_t a, uint32_t r0, uint32_t r1) {
    asm volatile("stmatrix.sync.aligned.m8n8.x2.shared.b16 [%0], {%1,%2};" ::"r"(a), "r"(r0), "r"(r1) : "memory");
}
__device__ __forceinline__ uint32_t movm_t(uint32_t a) {
    uint32_t d;
    asm volatile("movmatrix.sync.aligned.m8n8.trans.b16 %0, %1;" : "=r"(d) : "r"(a));
    return d;
}
__device__ __forceinline__ uint32_t lds32(uint32_t a) { uint32_t v; asm volatile("ld.shared.u32 %0, [%1];" : "=r"(v) : "r"(a) : "memory"); return v; }
__device__ __forceinline__ uint32_t ldsv32(uint32_t a) { uint32_t v; asm volatile("ld.volatile.shared.u32 %0, [%1];" : "=r"(v) : "r"(a) : "memory"); return v; }
__device__ __forceinline__ void sts32(uint32_t a, uint32_t v) { asm volatile("st.shared.u32 [%0], %1;" ::"r"(a), "r"(v) : "memory"); }
__device__ __forceinline__ uint4 lds128(uint32_t a) { uint4 v; asm volatile("ld.shared.v4.u32 {%0,%1,%2,%3}, [%4];" : "=r"(v.x), "=r"(v.y), "=r"(v.z), "=r"(v.w) : "r"(a) : "memory"); return v; }
__device__ __forceinline__ void sts128(uint32_t a, uint4 v) { asm volatile("st.shared.v4.u32 [%0], {%1,%2,%3,%4};" ::"r"(a), "r"(v.x), "r"(v.y), "r"(v.z), "r"(v.w) : "memory"); }

__device__ __forceinline__ void stg128(void* p, uint4 v) { asm volatile("st.global.v4.u32 [%0], {%1,%2,%3,%4};" ::"l"(p), "r"(v.x), "r"(v.y), "r"(v.z), "r"(v.w) : "memory"); }

__device__ __forceinline__ uint4 ldg128(const void* p) { uint4 v; asm volatile("ld.global.v4.u32 {%0,%1,%2,%3}, [%4];" : "=r"(v.x), "=r"(v.y), "=r"(v.z), "=r"(v.w) : "l"(p) : "memory"); return v; }
__device__ __forceinline__ uint2 ldg64(const void* p) { uint2 v; asm volatile("ld.global.v2.u32 {%0,%1}, [%2];" : "=r"(v.x), "=r"(v.y) : "l"(p) : "memory"); return v; }
__device__ __forceinline__ uint32_t ldg32(const void* p) { uint32_t v; asm volatile("ld.global.u32 %0, [%1];" : "=r"(v) : "l"(p) : "memory"); return v; }

__device__ __forceinline__ uint32_t pack2(float lo, float hi) {
    uint32_t r;
    asm("cvt.rn.bf16x2.f32 %0, %1, %2;" : "=r"(r) : "f"(hi), "f"(lo));
    return r;
}
__device__ __forceinline__ float bf_lo(uint32_t v) { return __uint_as_float(v << 16); }
__device__ __forceinline__ float bf_hi(uint32_t v) { return __uint_as_float(v & 0xFFFF0000u); }
__device__ __forceinline__ float rbf(float x) { return __uint_as_float(pack2(0.f, x) & 0xFFFF0000u); }
__device__ __forceinline__ float ex2(float x) { float r; asm("ex2.approx.ftz.f32 %0, %1;" : "=f"(r) : "f"(x)); return r; }

__device__ __forceinline__ float2 ln_finish(float sum, float sumsq) {
    const float m = sum * (1.0f / DM);
    const float v = fmaxf(fmaf(sumsq, 1.0f / DM, -m * m), 0.f);
    float s, r;
    asm("sqrt.approx.ftz.f32 %0, %1;" : "=f"(s) : "f"(rbf(rbf(v) + 1e-5f)));
    asm("rcp.approx.ftz.f32 %0, %1;" : "=f"(r) : "f"(rbf(s)));
    return make_float2(m, r);
}
__device__ __forceinline__ uint32_t ln_finish_packed(float sum, float sumsq) {
    const float m = sum * (1.0f / DM);
    const float v = fmaxf(fmaf(sumsq, 1.0f / DM, -m * m), 0.f);
    float s;
    asm("sqrt.approx.ftz.f32 %0, %1;" : "=f"(s) : "f"(rbf(rbf(v) + 1e-5f)));
    return pack2(s, m);
}
__device__ __forceinline__ float frsq(float x) { float r; asm("rsqrt.approx.ftz.f32 %0, %1;" : "=f"(r) : "f"(x)); return r; }
__device__ __forceinline__ float frcp(float x) { float r; asm("rcp.approx.ftz.f32 %0, %1;" : "=f"(r) : "f"(x)); return r; }
__device__ __forceinline__ bool elect_one() {
    uint32_t p;
    asm volatile("{\n.reg .pred p;\nelect.sync _|p, 0xffffffff;\nselp.u32 %0, 1, 0, p;\n}" : "=r"(p));
    return p != 0;
}
__device__ __forceinline__ void cluster_arrive_relaxed() { asm volatile("barrier.cluster.arrive.relaxed.aligned;" ::: "memory"); }
__device__ __forceinline__ void cluster_wait() { asm volatile("barrier.cluster.wait.aligned;" ::: "memory"); }
__device__ __forceinline__ unsigned long long ld_ll(const unsigned long long* p) {
    unsigned long long v;
    asm volatile("ld.relaxed.gpu.global.b64 %0, [%1];" : "=l"(v) : "l"(p) : "memory");
    return v;
}
__device__ __forceinline__ void st_ll(unsigned long long* p, uint32_t payload, uint32_t tag) {
    const unsigned long long v = (unsigned long long)payload | ((unsigned long long)tag << 32);
    asm volatile("st.relaxed.gpu.global.b64 [%0], %1;" ::"l"(p), "l"(v) : "memory");
}
__device__ __forceinline__ uint4 ld_ll4(const uint4* p) {
    uint4 v;
    asm volatile("{\n.reg .b128 t;\n.reg .b64 a, b;\nld.relaxed.gpu.global.b128 t, [%4];\nmov.b128 {a, b}, t;\nmov.b64 {%0, %1}, a;\nmov.b64 {%2, %3}, b;\n}"
                 : "=r"(v.x), "=r"(v.y), "=r"(v.z), "=r"(v.w) : "l"(p) : "memory");
    return v;
}
__device__ __forceinline__ void st_ll4(uint4* p, uint32_t x, uint32_t y, uint32_t z, uint32_t w) {
    asm volatile("{\n.reg .b128 t;\n.reg .b64 a, b;\nmov.b64 a, {%1, %2};\nmov.b64 b, {%3, %4};\nmov.b128 t, {a, b};\nst.relaxed.gpu.global.b128 [%0], t;\n}"
                 ::"l"(p), "r"(x), "r"(y), "r"(z), "r"(w) : "memory");
}

__device__ __forceinline__ void bulk_s2g(void* dst, uint32_t src, uint32_t bytes) {
    asm volatile("cp.async.bulk.global.shared::cta.bulk_group [%0], [%1], %2;" ::"l"(dst), "r"(src), "r"(bytes) : "memory");
}
__device__ __forceinline__ void bulk_commit() { asm volatile("cp.async.bulk.commit_group;" ::: "memory"); }
__device__ __forceinline__ void bulk_wait() { asm volatile("cp.async.bulk.wait_group 0;" ::: "memory"); }
__device__ __forceinline__ void fence_async_global() { asm volatile("fence.proxy.async.global;" ::: "memory"); }
__device__ __forceinline__ void fence_release() { asm volatile("fence.release.gpu;" ::: "memory"); }
__device__ __forceinline__ void fence_acquire() { asm volatile("fence.acquire.gpu;" ::: "memory"); }
__device__ __forceinline__ void ll_check5(uint4 (&f)[5], const uint4* p, uint32_t mark) {
#define LL_LD(i, a, b, c, d) "ld.relaxed.gpu.global.b128 q, [%20 + " #i "];\nmov.b128 {u, v}, q;\nmov.b64 {%" #a ", %" #b "}, u;\nmov.b64 {%" #c ", %" #d "}, v;\n"
    asm volatile("{\n.reg .pred p;\n.reg .b32 t, n, m;\n.reg .b128 q;\n.reg .b64 u, v;\nmov.u32 n, 0x7FFFF;\n"
                 "L:\nlop3.b32 t, %0, %4, %21, 0x7E;\nlop3.b32 t, t, %8, %21, 0xF6;\nlop3.b32 t, t, %12, %21, 0xF6;\nlop3.b32 t, t, %16, %21, 0xF6;\n"
                 "shr.u32 m, n, 18;\nand.b32 t, t, m;\nsetp.ne.u32 p, t, 0;\nvote.sync.any.pred p, p, 0xffffffff;\n@!p bra.uni D;\n"
                 LL_LD(0, 0, 1, 2, 3) LL_LD(512, 4, 5, 6, 7) LL_LD(1024, 8, 9, 10, 11) LL_LD(1536, 12, 13, 14, 15) LL_LD(2048, 16, 17, 18, 19)
                 "sub.u32 n, n, 1;\nbra.uni L;\nD:\n}"
                 : "+r"(f[0].x), "+r"(f[0].y), "+r"(f[0].z), "+r"(f[0].w), "+r"(f[1].x), "+r"(f[1].y), "+r"(f[1].z), "+r"(f[1].w), "+r"(f[2].x), "+r"(f[2].y),
                   "+r"(f[2].z), "+r"(f[2].w), "+r"(f[3].x), "+r"(f[3].y), "+r"(f[3].z), "+r"(f[3].w), "+r"(f[4].x), "+r"(f[4].y), "+r"(f[4].z), "+r"(f[4].w)
                 : "l"(p), "r"(mark) : "memory");
}
template<int TA, int TB>
__device__ __forceinline__ void wgmma_n192(float (&d)[96], uint64_t da, uint64_t db, int scale_d) {
  asm volatile("{\n.reg .pred p;\nsetp.ne.b32 p, %98, 0;\n"
    "wgmma.mma_async.sync.aligned.m64n192k16.f32.bf16.bf16 "
    "{%0, %1, %2, %3, %4, %5, %6, %7, %8, %9, %10, %11, %12, %13, %14, %15, %16, %17, %18, %19, %20, %21, %22, %23, %24, %25, %26, %27, %28, %29, %30, %31, %32, %33, %34, %35, %36, %37, %38, %39, %40, %41, %42, %43, %44, %45, %46, %47, %48, %49, %50, %51, %52, %53, %54, %55, %56, %57, %58, %59, %60, %61, %62, %63, %64, %65, %66, %67, %68, %69, %70, %71, %72, %73, %74, %75, %76, %77, %78, %79, %80, %81, %82, %83, %84, %85, %86, %87, %88, %89, %90, %91, %92, %93, %94, %95}, %96, %97, p, 1, 1, %99, %100;\n}\n"
    : "+f"(d[0]), "+f"(d[1]), "+f"(d[2]), "+f"(d[3]), "+f"(d[4]), "+f"(d[5]), "+f"(d[6]), "+f"(d[7]), "+f"(d[8]), "+f"(d[9]), "+f"(d[10]), "+f"(d[11]), "+f"(d[12]), "+f"(d[13]), "+f"(d[14]), "+f"(d[15]), "+f"(d[16]), "+f"(d[17]), "+f"(d[18]), "+f"(d[19]), "+f"(d[20]), "+f"(d[21]), "+f"(d[22]), "+f"(d[23]), "+f"(d[24]), "+f"(d[25]), "+f"(d[26]), "+f"(d[27]), "+f"(d[28]), "+f"(d[29]), "+f"(d[30]), "+f"(d[31]), "+f"(d[32]), "+f"(d[33]), "+f"(d[34]), "+f"(d[35]), "+f"(d[36]), "+f"(d[37]), "+f"(d[38]), "+f"(d[39]), "+f"(d[40]), "+f"(d[41]), "+f"(d[42]), "+f"(d[43]), "+f"(d[44]), "+f"(d[45]), "+f"(d[46]), "+f"(d[47]), "+f"(d[48]), "+f"(d[49]), "+f"(d[50]), "+f"(d[51]), "+f"(d[52]), "+f"(d[53]), "+f"(d[54]), "+f"(d[55]), "+f"(d[56]), "+f"(d[57]), "+f"(d[58]), "+f"(d[59]), "+f"(d[60]), "+f"(d[61]), "+f"(d[62]), "+f"(d[63]), "+f"(d[64]), "+f"(d[65]), "+f"(d[66]), "+f"(d[67]), "+f"(d[68]), "+f"(d[69]), "+f"(d[70]), "+f"(d[71]), "+f"(d[72]), "+f"(d[73]), "+f"(d[74]), "+f"(d[75]), "+f"(d[76]), "+f"(d[77]), "+f"(d[78]), "+f"(d[79]), "+f"(d[80]), "+f"(d[81]), "+f"(d[82]), "+f"(d[83]), "+f"(d[84]), "+f"(d[85]), "+f"(d[86]), "+f"(d[87]), "+f"(d[88]), "+f"(d[89]), "+f"(d[90]), "+f"(d[91]), "+f"(d[92]), "+f"(d[93]), "+f"(d[94]), "+f"(d[95])
    : "l"(da), "l"(db), "r"(scale_d), "n"(TA), "n"(TB));
}

template<int TA, int TB>
__device__ __forceinline__ void wgmma_n48(float (&d)[24], uint64_t da, uint64_t db, int scale_d) {
  asm volatile("{\n.reg .pred p;\nsetp.ne.b32 p, %26, 0;\n"
    "wgmma.mma_async.sync.aligned.m64n48k16.f32.bf16.bf16 "
    "{%0, %1, %2, %3, %4, %5, %6, %7, %8, %9, %10, %11, %12, %13, %14, %15, %16, %17, %18, %19, %20, %21, %22, %23}, %24, %25, p, 1, 1, %27, %28;\n}\n"
    : "+f"(d[0]), "+f"(d[1]), "+f"(d[2]), "+f"(d[3]), "+f"(d[4]), "+f"(d[5]), "+f"(d[6]), "+f"(d[7]), "+f"(d[8]), "+f"(d[9]), "+f"(d[10]), "+f"(d[11]), "+f"(d[12]), "+f"(d[13]), "+f"(d[14]), "+f"(d[15]), "+f"(d[16]), "+f"(d[17]), "+f"(d[18]), "+f"(d[19]), "+f"(d[20]), "+f"(d[21]), "+f"(d[22]), "+f"(d[23])
    : "l"(da), "l"(db), "r"(scale_d), "n"(TA), "n"(TB));
}

__device__ __forceinline__ void wgmma_rs80(float (&d)[40], const uint4& a, uint64_t db, int scale_d) {
  asm volatile("{\n.reg .pred p;\nsetp.ne.b32 p, %45, 0;\n"
    "wgmma.mma_async.sync.aligned.m64n80k16.f32.bf16.bf16 {%0,%1,%2,%3,%4,%5,%6,%7,%8,%9,%10,%11,%12,%13,%14,%15,%16,%17,%18,%19,%20,%21,%22,%23,%24,%25,%26,%27,%28,%29,%30,%31,%32,%33,%34,%35,%36,%37,%38,%39}, {%40,%41,%42,%43}, %44, p, 1, 1, 1;\n}\n"
    : "+f"(d[0]), "+f"(d[1]), "+f"(d[2]), "+f"(d[3]), "+f"(d[4]), "+f"(d[5]), "+f"(d[6]), "+f"(d[7]), "+f"(d[8]), "+f"(d[9]), "+f"(d[10]), "+f"(d[11]), "+f"(d[12]), "+f"(d[13]), "+f"(d[14]), "+f"(d[15]), "+f"(d[16]), "+f"(d[17]), "+f"(d[18]), "+f"(d[19]), "+f"(d[20]), "+f"(d[21]), "+f"(d[22]), "+f"(d[23]), "+f"(d[24]), "+f"(d[25]), "+f"(d[26]), "+f"(d[27]), "+f"(d[28]), "+f"(d[29]), "+f"(d[30]), "+f"(d[31]), "+f"(d[32]), "+f"(d[33]), "+f"(d[34]), "+f"(d[35]), "+f"(d[36]), "+f"(d[37]), "+f"(d[38]), "+f"(d[39])
    : "r"(a.x), "r"(a.y), "r"(a.z), "r"(a.w), "l"(db), "r"(scale_d));
}

__device__ __forceinline__ void wgmma_ss80(float (&d)[40], uint64_t da, uint64_t db) {
  asm volatile("wgmma.mma_async.sync.aligned.m64n80k16.f32.bf16.bf16 {%0,%1,%2,%3,%4,%5,%6,%7,%8,%9,%10,%11,%12,%13,%14,%15,%16,%17,%18,%19,%20,%21,%22,%23,%24,%25,%26,%27,%28,%29,%30,%31,%32,%33,%34,%35,%36,%37,%38,%39}, %40, %41, 1, 1, 1, 0, 1;"
    : "+f"(d[0]), "+f"(d[1]), "+f"(d[2]), "+f"(d[3]), "+f"(d[4]), "+f"(d[5]), "+f"(d[6]), "+f"(d[7]), "+f"(d[8]), "+f"(d[9]), "+f"(d[10]), "+f"(d[11]), "+f"(d[12]), "+f"(d[13]), "+f"(d[14]), "+f"(d[15]), "+f"(d[16]), "+f"(d[17]), "+f"(d[18]), "+f"(d[19]), "+f"(d[20]), "+f"(d[21]), "+f"(d[22]), "+f"(d[23]), "+f"(d[24]), "+f"(d[25]), "+f"(d[26]), "+f"(d[27]), "+f"(d[28]), "+f"(d[29]), "+f"(d[30]), "+f"(d[31]), "+f"(d[32]), "+f"(d[33]), "+f"(d[34]), "+f"(d[35]), "+f"(d[36]), "+f"(d[37]), "+f"(d[38]), "+f"(d[39])
    : "l"(da), "l"(db));
}

__device__ const __align__(1024) uint32_t c_fft[11264] = {
0x2ddc2dba,0x2fe62eb5,0x2ed02eb5,0xafffaf6e,0x2e1f2dfe,0x2e3f2fbc,0x2f022ee9,0xad27af30,0x2e5e2e3f,0x1fd92b5e,0x2f302f1a,0x244ea875,0x2e992e7c,0xad96a993,0x2f5a2f46,0x2e992c32,
0xad00ad72,0xa17eac32,0xa17ea515,0xabb79cb6,0xac07ac87,0x2dfe29f1,0x1fd99648,0xafedae99,0xa9f1ab05,0x2fd42fbc,0x26a1244e,0xad96af91,0xa765a8d5,0x2aaa2e3f,0x29932875,0x2515a8d5,
0xae99adfe,0xb000aee9,0xaf6eafbc,0x2c872f30,0xaf80af1a,0xac32af02,0xae7caf02,0xaaaa217e,0xaff4afc9,0x2b5e9cb6,0xad27addc,0xaff4ae7c,0xafedb000,0x2ffc2eb5,0xab05ac5d,0xacd8af5a,
0x2c072d27,0x9fd92bb7,0xadfead00,0x2fed2e1f,0x25db2993,0xaf6eacb0,0xaf6eaed0,0x2c5d2f46,0xa5151648,0xaddcafdd,0xafffafd4,0xac321648,0xabb7a934,0x28d5a814,0xafa0afed,0xaff4af30,
0x2f302e3f,0x2fed2f1a,0x28142b5e,0x2934a875,0x30002fc9,0x26a12ddc,0xa5db1cb6,0x30002e7c,0x2f462fd4,0xaed0aa4e,0xacb0aa4e,0x29932e99,0x2d272e5e,0xae3faffc,0xaf02adfe,0xae1fa814,
0xa9f1acd8,0x26a1ab05,0x2fd42ffc,0xad96afed,0x2515a30e,0x2fff2e1f,0x2ddc2f1a,0x2c32a30e,0x2d272aaa,0x28752e7c,0x28752c32,0x2fa02f80,0x2f912e99,0xaee9a9f1,0xa8141648,0x9fd92c87,
0xafa0ae7c,0xafafaf46,0x2d002993,0xafa0ac32,0xaf91b000,0x244eac5d,0x2fbc2eb5,0xab05af5a,0xac87ae5e,0x30002dfe,0x2f6e2ffc,0x2e992814,0x1cb6a875,0x25152e1f,0x2c322e1f,0x2d722ff4,
0x27652c87,0xa9932a4e,0xaaaaadba,0xa5152c87,0xabb7a44e,0xafa0af30,0x28d59fd9,0xaff4ae5e,0xaf91ae1f,0x2814abb7,0x2ee92d00,0x1fd9ad27,0xaf5aafff,0x2fd42ed0,0x2fd42fe6,0x30002ddc,
0x2f462f6e,0x2c322fdd,0x2e7c2fdd,0xa993b000,0xab5e2934,0xafafacd8,0xad00244e,0x2f1a2dfe,0xaee9afaf,0x2f30a17e,0xadfeaff8,0xafbca30e,0x2c5da765,0xa9f12ddc,0x2d969cb6,0x2c5dacb0,
0x2bb7a993,0x2f1aa515,0x2f1a2765,0xaff4aaaa,0x2e5e2fd4,0xab052dba,0x29342f6e,0x2ee9a6a1,0xadba1fd9,0xa5dbafed,0xafddac07,0xaa4e2dfe,0xacb0aff8,0x2ddc2f02,0x9cb6ae3f,0xa765aff8,
0xaeb5af91,0xaa4eafed,0x9648ae5e,0xac5d2d4d,0x2ddca17e,0x2e7c2e3f,0x2fc92e3f,0x1cb6afa0,0x2bb72fe6,0xaff8a993,0xab5e2aaa,0x2bb72fc9,0xafbcaa4e,0x2f30a5db,0xadfeafdd,0xaee9adba,
0xacd828d5,0xaf91230e,0xaf30af02,0x2c072fa0,0xac5dafff,0x2dbaac32,0x2dbaa515,0xae99addc,0x2fc929f1,0xa9932eb5,0x2aaa2fdd,0x2fe629f1,0xa30e2dfe,0xa17eafed,0xaff8ac07,0xafaf1fd9,
0x2dfe2faf,0x28142ff8,0xae5e217e,0x2ffc230e,0xaf5aa515,0xac87af46,0xa6a1af80,0xaf5a2765,0x1cb6ae99,0x2e7c2dba,0x2fc92dba,0x2ddcac5d,0x2f1a2ee9,0xafafab05,0xad002934,0xab5e2e5e,
0x2dbaa814,0x2fdd9fd9,0x25db2f91,0x2a4eaee9,0x27652faf,0xaf4628d5,0xaf80ae1f,0xa5152faf,0xafa0addc,0x2e3fac32,0x2e3fa515,0xa17eafff,0x2dfea6a1,0xacd82dba,0x244e2f6e,0x29342fd4,
0xad27afc9,0xa30eafff,0x2faf2d72,0xad27ae7c,0x2ffc2a4e,0x28142fdd,0xae5e25db,0x2dfe2dba,0xac5d2c07,0xaa4eaf91,0x9648af30,0xaeb5acd8,0xa993aff4,0x2c322f1a,0x2e7c2f1a,0x2f462bb7,
0xae7c26a1,0xafff1648,0x2d72aa4e,0xafc926a1,0x230eaee9,0x2ff89fd9,0x217e2f91,0x2fafa814,0x2d4d2fa0,0xafed230e,0xae5eaf02,0xaf9128d5,0xb000aaaa,0x2fdda515,0x2fdd2765,0x2f6ea993,
0x9cb63000,0xacb02fd4,0xa7652fd4,0x2ddcaf5a,0x217eaffc,0x2ff4ac07,0x2875afbc,0xaff82934,0xa44e2ff4,0xadfea8d5,0xa9342fa0,0x2cd82bb7,0x25dbafe6,0x16482f46,0x29f1af80,0x25dbafc9,
0x2ff41cb6,0x2e1f2765,0x2e1f2cb0,0xa875addc,0xafbca5db,0x1fd9af5a,0xad4dad96,0xacd82fdd,0x2f5a2934,0xaeb52ee9,0x2c5d2e5e,0x3000ab05,0xaed0ab5e,0x2f80a30e,0xaaaaaf02,0xacb0ab5e,
0x25dbaffc,0x2d96afbc,0x2f5aac07,0xafdd2934,0xaaaa2fa0,0xafc92875,0xafe62875,0x29932d27,0x2d00aed0,0x28d52d72,0x2ff89cb6,0x2d00afe6,0xae5e2d96,0x2d4dafd4,0xaf91a6a1,0xafed29f1,
0xafbca17e,0xad4da875,0x1fd9aff4,0xacd82ff8,0x2e992aaa,0xaa4e2fe6,0xaa4e2fc9,0x2fd4a993,0xacb0ad96,0x2fffac87,0x2d72aeb5,0xa765ad96,0x28752f30,0xab5eac07,0xaf1a2cd8,0xae3f2f91,
0xa9342ff4,0xae5e2fa0,0xaee9a8d5,0x2b052bb7,0x2d96aed0,0x2eb59cb6,0x2c872d72,0x2d96afe6,0xaf802c5d,0x2765af6e,0xa515af6e,0xaf4625db,0x2ff8a44e,0xaff42d4d,0xa8752ffc,0xa17e2ee9,
0x2f5a244e,0x2c5d2934,0xaeb52dfe,0x3000acd8,0xacb0ad00,0x2d72aff8,0x2fffa8d5,0xa765ad00,0x217e2f80,0xaf022515,0xaf02a765,0xaf1a2f46,0x2b05afdd,0xa8142f5a,0x2c072d96,0x2d4d25db,
0x2b5eafe6,0x2f02af80,0x230e2f46,0x2b5eafc9,0xaf302d96,0xacd8a6a1,0x2c07afd4,0xaf9129f1,0x2fdda44e,0xad962ffc,0xaf5a2d4d,0xa5db2ee9,0xad72abb7,0x2e7ca17e,0x2fc9a17e,0x2fffad00,
0xaed0a5db,0xaaaaa9f1,0x2f809648,0xacb0a5db,0x28752e5e,0xaf1a2f91,0xab5ead4d,0xae3f2fed,0x2b05aff8,0x2c072875,0xa8142ff4,0x2d4d217e,0xaf6e2d72,0x2eb5afc9,0x2eb5ae7c,0x2dbaafff,
0xaf802f5a,0xafc92e99,0xafe62e99,0x2f46ad96,0x28d52b05,0xaf022fed,0x230e2cd8,0x2fa0affc,0x2fbcaf02,0xa9342d27,0x2ffcae1f,0x2c07ae3f,0xa6a1ac32,0x2a4e9cb6,0x9648ad72,0xa6a1a515,
0x28752aaa,0xa8d52cb0,0xa8d52ed0,0x2e3faf80,0x2fedaeb5,0x29349648,0x2f30aa4e,0x2814ac5d,0x1648ad4d,0x2e99acd8,0x2c87afbc,0xa9f11fd9,0xafe62d27,0x2fffafaf,0xaddc230e,0xaed02d27,
0x2fd4af30,0x2f6eae5e,0x2dbaa44e,0xa6a19fd9,0x1cb6ad27,0x2fe6aff4,0x2ed0aff4,0xad722b5e,0xafaf2cb0,0x2e1faf46,0xa8d5a993,0xafaf2ed0,0xac072f6e,0x2934ac87,0xaffc2e99,0xafbc3000,
0xa44eab5e,0x2b05ad00,0x2f91afaf,0xafbc2f1a,0xafd42d72,0x1648a765,0x1648acb0,0xafdd2fff,0xac322f5a,0xaaaa26a1,0xaf802c87,0xae7c2f5a,0x2d009fd9,0xae1f2cd8,0xad272fbc,0xabb72d4d,
0xaffc2f02,0xaee92e1f,0x244ead27,0xad4d2e3f,0xa9f12e7c,0xafdd2f80,0xaeb52aaa,0xa9f12c32,0x2d72a5db,0xafe63000,0xaed03000,0x9cb626a1,0x2fa0afbc,0xaf022f91,0x230e2b05,0x28d5a44e,
0x96482c07,0xac872d4d,0xae992b05,0x29f1a814,0x2ed0abb7,0xa9932b5e,0xaf462ff8,0x2cb0abb7,0x2f1aafff,0xa30e2765,0xa30e2cb0,0x2e1fad72,0x1fd9ac5d,0x244e9648,0x2e5eaa4e,0x2f30aeb5,
0x2ff8aed0,0x2e3faddc,0xaf022fff,0x2ff8afe6,0x2d4daf6e,0x2ee9ae99,0xa44e2c87,0x2ffcb000,0xa6a1a814,0x2f6eaf30,0x2dbaa934,0x2fd4afed,0xaf462d00,0x2fc9afa0,0x2fe6afa0,0x2f80afaf,
0x2515ac5d,0x2d72ad96,0x1cb629f1,0x2c32ac5d,0xad002814,0x2d27ad4d,0x2e1fab05,0x2bb7ac07,0xaffc2f1a,0x2cd8ad00,0x2fedafaf,0x2b05ab5e,0xadba2f80,0x2c87acb0,0x2c87aed0,0x2a4eaaaa,
0x2f802f6e,0x2fc92fdd,0x2fe62fdd,0xaf46b000,0x2fa02f91,0x2bb72e5e,0x2ff42fed,0xa8d5ad4d,0x2fbc2faf,0xa934217e,0x2ffc2ff8,0x2c07230e,0x2fd42fc9,0xaf5aad72,0x30002fff,0x2fd42e7c,
0x2bb72aaa,0x2f1a2cb0,0x2f1a2ed0,0xaff4af80,0x2cd82c5d,0x2f303000,0x2f912f5a,0xac07aeb5,0x2dba2d4d,0x25db2cd8,0x2fdd2fbc,0x2a4e9fd9,0x2e7c2e1f,0xad72a875,0x2fff2ff4,0x2fc92e1f,
0xa6a1a934,0x29f1a44e,0x2d962cd8,0xafd4adfe,0x1cb6a17e,0x2fe62e3f,0x2ed02e3f,0xad72afa0,0x28752515,0x2d272f80,0x2fa02f46,0x2875a765,0x2c072a4e,0xa93425db,0x2ffc2fdd,0x2fbc2dba,
0xae5eaf1a,0xa934ae3f,0x2b052875,0xaee9ab5e,0xac5dad72,0x2dba2765,0x2dba2cb0,0xae99afff,0xa765aa4e,0x2f802fd4,0x2f462e99,0x2515aa4e,0x230e9fd9,0x217e2cd8,0x2ff82fbc,0x2faf2d4d,
0xaffcafaf,0xaee9aff8,0x244ea17e,0xad4da30e,0xaf6eafe6,0x25dbaaaa,0x2c5d2993,0xaf6eafc9,0xad72ae99,0x2fe62dba,0x2ed02dba,0x1cb6ac5d,0xa8d5ac07,0x2bb72f30,0x2ff42f91,0x2fa02cd8,
0xadbaac07,0xafddad4d,0xa5dbab05,0xaa4e2814,0xafc9af02,0xaaaaaf1a,0x2993217e,0xafe6af02,0xafa0afff,0x2e3f2765,0x2e3f2cb0,0xa17ead72,0xad4daeb5,0x2e5e3000,0x2fed2f5a,0x2f912c5d,
0xa17e2765,0xad001cb6,0xabb7addc,0xa17e2cb0,0xad4daa4e,0xaee9afdd,0x244ea5db,0xaffcadba,0xafd4aee9,0x29f1a934,0x2d962b05,0xa6a1ae5e,0xaf46aff4,0x2fc92f1a,0x2fe62f1a,0x2f802bb7,
0x2cb02eb5,0x1cb62dba,0xaddcaf6e,0x27652eb5,0xa30e2814,0xaff8ad4d,0xa17eab05,0xafafac07,0xadfeab5e,0xa44eae3f,0x2cd82875,0xa934af1a,0xb000af80,0x2fdd2cb0,0x2fdd2ed0,0x2f6e2aaa,
0x2d723000,0x25152fd4,0x2c322fd4,0x1cb6af5a,0xae1f9fd9,0xae3faee9,0xaf02a814,0x2d272f91,0xacd8aff4,0x2ffc28d5,0xab05afa0,0xafedabb7,0x2e992515,0xad962aaa,0x2f5a2993,0x2e99a765,
0x2ff42ddc,0x2e1f2ed0,0x2e1f2fe6,0xa875afff,0xa8142c87,0xaffca9f1,0xadfe1648,0x2e5e2e99,0xaf5aaf30,0x2eb5a814,0xac5dafed,0xb000a934,0x2c32a8d5,0xa9932e3f,0x2f462875,0x2e7ca8d5,
0x2e991fd9,0x30002814,0x2f6e2ee9,0xac87af91,0x29932fa0,0xaed02875,0xacb02875,0x2f462d27,0xaff4ac32,0x2b5eaddc,0xad27afff,0xaff4a515,0x244ead96,0x1fd92fd4,0x2f3026a1,0x2e5ea9f1,
0x2814ad27,0x2dfeabb7,0x2ffc2d00,0xae5eae1f,0x2e992f80,0xaa4e2e7c,0xaa4e2c32,0x2fd42aaa,0xae7c1648,0x9cb6afdd,0xaddcafd4,0xafc91648,0xa875af91,0x2b5e2fbc,0x2f1a244e,0x2e3fab05,
0xab05aff4,0x244eafa0,0x2fbc28d5,0xaf91abb7,0x30002c32,0x26a12fff,0xa5db2ddc,0x30002515,0xaaaa2c5d,0xac32af6e,0xae7caf6e,0xaf8025db,0xad27afed,0x2e3f2dfe,0x2f021fd9,0x2e1fac07,
0xaf5aae5e,0xac5daf30,0x2eb59fd9,0xb000a44e,0x2e7ca30e,0x2ddc2e1f,0x1cb62f1a,0x2fc9a30e,0x217e2f46,0xaf02acb0,0xaf02aed0,0xaf1a2993,0xaf30ae99,0x2fbc29f1,0x2ee99648,0x2dfeac87,
0xafa0a515,0xafafa993,0x2d00aaaa,0xafa02765,0x2934ad96,0x2fed26a1,0x28142fd4,0x2f30a9f1,0x2c872fed,0xb0009fd9,0xaf6eadfe,0xae992c07,0xafffabb7,0x2fe6a17e,0x2ed0a17e,0x2ddcad00,
0xac322c87,0xaf462a4e,0x2993adba,0xae7c2c87,0xa875afed,0x2f1aab05,0x2b5e2ffc,0x2e3facd8,0x2f302e1f,0xaee92bb7,0xafbcad00,0xadfe2d27,0xaf6e9cb6,0x2eb5ac32,0x2eb5a515,0x2dbaad72,
0xaaaa2f5a,0xaed02e99,0xacb02e99,0x2f80ad96,0x2b5eaf30,0x2fafa44e,0x2d00ae5e,0xaf1a9fd9,0xac072f02,0xab05ad27,0xad4d2e1f,0x28142e3f,0x2c5daed0,0xa9f12fff,0x2d96addc,0x2c5dafe6,
0x28752f80,0xa8d52fe6,0xa8d52fc9,0x2e3faf46,0xa44eafd4,0x2f91adba,0x2b05af6e,0xafbc26a1,0x96482ffc,0xae99a44e,0xac872ee9,0x29f12d4d,0x2515aff8,0x1cb62f02,0x2d72ae3f,0x2c32aff8,
0x2eb52b05,0x2a4e2cd8,0x16482fed,0x2c5daffc,0xad72ad27,0x2cb0aff4,0x2765aff4,0xafff2b5e,0x2bb72e7c,0xaff82aaa,0xab5e2f80,0x2bb72c32,0xa814af6e,0x2b052c87,0x2d4dae99,0x2c07b000,
0x2feda8d5,0x2f30a30e,0x29342f02,0x2814afa0,0xafd49cb6,0x1648aed0,0x1648afe6,0xafdd2d72,0x2ed029f1,0xaf462eb5,0xa9932fdd,0x2cb029f1,0xad00ad4d,0x2e1f244e,0x2d27aee9,0x2bb7affc,
0x2d4daf02,0x2fbcae1f,0x2cd82d27,0x9fd9ae3f,0xaf5a2cb0,0xac87a993,0xa6a1af46,0xaf5a2ed0,0x2fffa5db,0xacb03000,0xa7653000,0x2d7226a1,0xaf1aa814,0x2fafa934,0x2d00af30,0x2b5eafed,
0x1648afbc,0x2c87affc,0x2e992934,0xa9f1ac07,0xac322faf,0xaf8028d5,0xaaaaae1f,0xae7c2faf,0x2f1aad72,0xa30e2ed0,0xa30e2fe6,0x2e1f1cb6,0xaffc26a1,0x2fedadba,0x2cd8af6e,0x2b05afd4,
0xad27ac32,0xa30ead72,0x2faf9cb6,0xad27a515,0x1fd92f6e,0xafbc2e99,0xacd8ac87,0xad4d3000,0x2c5dafbc,0x2a4e2b05,0x16482f91,0x2eb5a44e,0xaf802d00,0x2ed0afa0,0x2cb0afa0,0x2aaaafaf,
0xafe626a1,0xaddc1648,0x2fffaa4e,0xaed026a1,0x2d002c07,0xad272ffc,0xae1fa934,0xabb72fbc,0x1fd9afa0,0x2e5ea30e,0x244e2f02,0x2f30a8d5,0xadba2f46,0x2c87afe6,0x2c87afc9,0x2a4eaf80,
0xafff2d96,0xae7c2c5d,0xafc92c5d,0x2d72a9f1,0xa17e2dfe,0xaff42fbc,0xa8752ee9,0x2ff8af30,0x2fedad00,0xad4d2f1a,0x2f91ab5e,0x2e5eafaf,0x25dbae7c,0x16482993,0x29f1af46,0x25dbac32,
0xae3f2fff,0xaff82fc9,0xaff82e7c,0x2f02ad72,0x2c0725db,0xadfe2f5a,0x9fd92d96,0x2fedafdd,0x2f6eaf91,0xa6a12c07,0x2fd4acd8,0x2dbaaf30,0xa765ab5e,0x2aaaa30e,0x2993af02,0x2515ab5e,
0xa5db2dfe,0xad962ee9,0xaf5a2fbc,0x2fddaf30,0x2f46ab5e,0xa7652bb7,0x25152bb7,0x2f80aff8,0x2d00afc9,0x28d59cb6,0x2ff8addc,0x2d00ae7c,0xacd89648,0x2dfeac5d,0x2934aeb5,0x244eaa4e,
0x2c07217e,0x9fd92875,0xadfe2ff4,0x2fedaff8,0x2fddaf46,0x29f1a515,0x29f12765,0x2eb5af80,0x2515ad96,0x2ddcac87,0x2fffaeb5,0x2c32ad96,0xaf022b05,0x2fa0aee9,0x28d5ae5e,0x230ea934,
0x2f91ad00,0x2cd8ab5e,0xac072f1a,0x2f30afaf,0x2d96afc9,0x2eb5addc,0x2c879cb6,0x2d96ae7c,0xa993a6a1,0x2fc9af5a,0x2fe6af5a,0x2aaaac87,0xaff82e5e,0x2ff4affc,0x2875adfe,0x217ea814,
0x2f6eafed,0x2fd4af91,0xa6a12d4d,0x2dbaae5e,0x2515ad00,0x2fffaff8,0x2ddca8d5,0x2c32ad00,0xae1f2993,0x2fafafe6,0x2fafafc9,0x28d5aaaa,0xaf912fdd,0x2ee9af5a,0x2814ad96,0x1fd9a5db,
0x2b5eae7c,0x2f02af46,0x230e2993,0x2b5eac32,0xab059648,0x2e5eaeb5,0x2ee9ac5d,0x2934aa4e,0xafdd2e5e,0x2d96adfe,0x2f5aaffc,0x25dba814,0xaddc2faf,0x2cb0ad27,0x2765ad27,0x1cb6a30e,
0xa765a5db,0x2993a9f1,0x2aaa9648,0x2515a5db,0xaf022cd8,0x28d5a934,0x2fa0adfe,0x230ea44e,0xaf912ff8,0x2814a875,0x2ee9aff4,0x1fd9a17e,0xaa4e2ddc,0x26a1a765,0x26a1acb0,0x16489cb6,
0x2d722d96,0x25152c5d,0x2c322c5d,0x1cb6a9f1,0x2d272d4d,0xad00a814,0x2bb72c07,0x2e1f2b05,0x2cd82d00,0xaffcaf1a,0x2b052b5e,0x2fed2faf,0x2c872cb0,0xadbaaf80,0x2a4e2aaa,0x2c872ed0,
0x2e3f2ddc,0x2ff82ed0,0x2ff82fe6,0xaf02afff,0x2ee92e99,0x2d4d2f6e,0x2ffc3000,0xa44eac87,0x2f6e2f30,0xa6a12814,0x2fd42fed,0x2dba2934,0x2fc92fa0,0xaf46ad00,0x2f802faf,0x2fe62fa0,
0xac87ad4d,0x9648ac07,0x29f12814,0xae99ab05,0xa993ab5e,0x2ed02bb7,0x2cb02bb7,0xaf46aff8,0xa30ea765,0x2f1a2fff,0x2e1f2d72,0xa30eacb0,0x244e1648,0x1fd92c5d,0x2f302eb5,0x2e5e2a4e,
0xaee9ae1f,0xaffcaf02,0xad4dae3f,0x244e2d27,0xafddaf80,0xa9f1ae7c,0xa9f1ac32,0xaeb5aaaa,0xafe6b000,0x2d7225db,0x9cb6a6a1,0xaed0b000,0xaf02af91,0x2fa02fbc,0x28d5244e,0x230eab05,
0x2b052d00,0xa44e2b5e,0xafbcaf1a,0x2f912faf,0x16482765,0xafd4ad72,0xafddafff,0x16482cb0,0xaaaaa6a1,0xac32af5a,0xae7caf5a,0xaf80ac87,0xae1facd8,0x2d001fd9,0xabb7ad4d,0xad27afbc,
0x2f6e2e5e,0x2fd42f30,0xa6a11fd9,0x2dba244e,0x2fe62ff4,0x1cb62d27,0xad72ab5e,0x2ed02ff4,0x2e1f2f46,0xafafacb0,0xafafaed0,0xa8d52993,0x29342c87,0xac07af6e,0xafbcb000,0xaffcae99,
0xa8d5acb0,0x2875aaaa,0x2e3f2f80,0xa8d5aed0,0x29341648,0x2fed2eb5,0x28142c5d,0x2f302a4e,0x2e992cd8,0x16482d4d,0xa9f19fd9,0x2c872fbc,0x2fff2faf,0xafe6ad27,0xaed0ad27,0xaddca30e,
0xafc9ae99,0xaf80af5a,0x2f462d96,0xafe6ae99,0xaf02afed,0x28d5ab05,0x2fa02ffc,0x230eacd8,0xa934ad27,0x2fbc2f02,0x2c072e3f,0x2ffc2e1f,0x2a4e1cb6,0xa6a12c32,0xa6a12515,0x96482d72,
0xaaaa29f1,0xaed025db,0xacb025db,0x2f801648,0xaf1aaf91,0x2875ae5e,0xae3fafed,0xab5e2d4d,0x2c07a875,0x2b052ff8,0x2d4da17e,0xa814aff4,0x2eb52fc9,0xaf6ead72,0x2dba2fff,0x2eb52e7c,
0x2f022f80,0x2b5e2fe6,0x2b5e2fc9,0x230eaf46,0xacd826a1,0xaf30ad96,0xaf91a9f1,0x2c072fd4,0xad96affc,0x2fdd244e,0xa5dbaee9,0xaf5aad4d,0x2e7c217e,0xad722bb7,0x2fff2d00,0x2fc9217e,
0x2c5da934,0x2f5aa44e,0x30002cd8,0xaeb5adfe,0x2d722ff8,0xacb02d00,0xa7652d00,0x2fff28d5,0xaf02a515,0x217eaf80,0xaf1aaf46,0xaf022765,0xa814af5a,0x2b052fdd,0x2d4da5db,0x2c07ad96,
0xae5eafa0,0xa934aff4,0x2b05abb7,0xaee928d5,0x2eb51cb6,0x2d962ed0,0x2d962fe6,0x2c87ad72,0x27652f6e,0xaf80ac5d,0xaf46a5db,0xa5152f6e,0xaff4ad4d,0x2ff8244e,0xa17eaee9,0xa875affc,
0xad4d2875,0xafbc217e,0xacd8aff8,0x1fd92ff4,0xaa4eafe6,0x2e99aaaa,0x2fd42993,0xaa4eafc9,0x2fff2c87,0xacb02d96,0xa7652d96,0x2d722eb5,0xab5e2c07,0x2875af30,0xae3faf91,0xaf1aacd8,
0x2d962fbc,0x25db2ffc,0xafdda934,0x2f5a2c07,0xafc9a875,0xaaaaafa0,0x2993ad27,0xafe6a875,0x28d5ad72,0x2d002ed0,0x2d002fe6,0x2ff81cb6,0x2d4d2fd4,0xae5ead96,0xafeda9f1,0xaf9126a1,
0x2e1fa765,0x2ff49cb6,0xa8752ddc,0x2e1facb0,0x1fd92f5a,0xafbc25db,0xacd8afdd,0xad4d2d96,0xaeb5aee9,0x2f5aa934,0x30002b05,0x2c5dae5e,0x2f80230e,0xaed02b5e,0xacb02b5e,0xaaaa2f02,
0xacb0afd4,0x9cb6b000,0x2ddc2f5a,0xa765afd4,0x2ff42c07,0x217e2ffc,0xaff8a934,0x28752fbc,0xadfe28d5,0xa44eaff4,0x2cd8abb7,0xa934afa0,0x1648af46,0x25db2fe6,0x25db2fc9,0x29f12f80,
0xafff9648,0xae7ca6a1,0xafc9a6a1,0x2d722a4e,0x2ff81fd9,0x230e2ee9,0x2faf2814,0x217eaf91,0xafeda30e,0x2d4dafa0,0xaf91a8d5,0xae5e2f02,0x2fdd2515,0xb0002aaa,0x2f6e2993,0x2fdda765,
0xa30e2fff,0xad272fc9,0xad272e7c,0x2fafad72,0x2814afdd,0x2ffcaa4e,0x2dfeadba,0xae5ea5db,0xaa4e2f91,0xac5dac07,0xaeb52cd8,0x96482f30,0x2c32af1a,0xa9932ff4,0x2f46abb7,0x2e7caf1a,
0x2fdd1fd9,0x2dba2814,0x2a4e2ee9,0x25dbaf91,0xaf46a8d5,0x2765afaf,0xa515afaf,0xaf802e1f,0x2e3f2c32,0xafa02ddc,0xa17e2fff,0x2e3f2515,0xacd8adba,0x2dfe26a1,0x2934afd4,0x244eaf6e,
0x2814aff8,0x2dfeafaf,0x2ffca30e,0xae5ea17e,0xac872f46,0xaf5a2515,0xaf5aa765,0xa6a12f80,0x2e7cadba,0x1cb62e99,0x2ddc2c5d,0x2fc9adba,0xafaf2b05,0x2f1aaee9,0xab5eae5e,0xad00a934,
0xaf91a30e,0xacd8a8d5,0x2c07afa0,0xaf302f02,0x2dba2c32,0xac5d2fff,0xae992ddc,0x2dba2515,0xa993aeb5,0x2fc9a9f1,0x2fe6a9f1,0x2aaaafdd,0xa17e2fed,0xa30eadfe,0xafaf9fd9,0xaff82c07,
0xaa4e2fed,0xaeb52f91,0xac5dad4d,0x96482e5e,0x2e7cae3f,0x2ddc217e,0x1cb62fa0,0x2fc9ae3f,0xaff82993,0x2bb7afe6,0x2bb7afc9,0xab5eaaaa,0x2f3025db,0xafbc2a4e,0xaee92dba,0xadfe2fdd,
0x2f1a2515,0x2bb72993,0xaff42aaa,0x2f1aa765,0xab05adba,0x2e5eafd4,0x2ee926a1,0x2934af6e,0xa5db2fed,0xadba9fd9,0xaa4eadfe,0xafdd2c07,0x2ddcaf02,0xacb02ff8,0xa7652ff8,0x9cb62e3f,
0x2c32afdd,0x2f46af6e,0xa9933000,0x2e7cafdd,0xafaf2cd8,0xab5ea934,0x2f1aadfe,0xad00a44e,0x2f30217e,0xaee92faf,0xafbc230e,0xadfe2ff8,0xa9f1addc,0x2c5d2765,0x2c5d2cb0,0x2d961cb6,
0xa993aa4e,0x2765ac87,0xa515ac87,0xaaaa2dba,0xafa02f30,0xabb7244e,0xaff42e5e,0x28d51fd9,0x28142bb7,0xaf912e1f,0x1fd92d27,0x2ee9ad00,0x2fd4aed0,0xaf5a2fff,0x3000addc,0x2fd4afe6,
0xafaf2f46,0xafa02e7c,0xafa02c32,0x2d00a993,0x244e2c5d,0xaf913000,0xab052f5a,0x2fbcaeb5,0x3000adfe,0xac872e5e,0x2e99a814,0x2f6eaffc,0x2515ae1f,0x1cb62875,0x2d72aff4,0x2c32ae1f,
0x26a12b05,0xa9f12cd8,0xad962fed,0x2fd4affc,0x2fffae1f,0x2515230e,0x2c32230e,0x2ddcaf1a,0x2875ae7c,0x2d27aaaa,0x2fa0af80,0x2875ac32,0xaee929f1,0x2f91ae99,0x9fd9ac87,0xa8149648,
0x2fedaf1a,0x2f30ae3f,0x29342875,0x2814ab5e,0x26a1addc,0x3000afc9,0x3000ae7c,0xa5db9cb6,0xaed02a4e,0x2f46afd4,0x2993ae99,0xacb02a4e,0xae3f2ffc,0x2d27ae5e,0xae1f2814,0xaf022dfe,
0x9fd9abb7,0x2c07ad27,0x2fedae1f,0xadfe2d00,0xaf6e2cb0,0x25dba993,0x2c5daf46,0xaf6e2ed0,0xaddc2fdd,0xa5159648,0xac329648,0xafff2fd4,0x28d52814,0xabb72934,0xaff42f30,0xafa02fed,
0xb0002ee9,0xae992dfe,0x2c87af30,0xaf6e2fbc,0xac322f02,0xaf802f1a,0xaaaaa17e,0xae7c2f02,0x2b5e1cb6,0xaff42fc9,0xaff42e7c,0xad272ddc,0x2ffcaeb5,0xafed3000,0xacd82f5a,0xab052c5d,
0xa17e2c32,0xad002d72,0xabb71cb6,0xa17e2515,0x2dfea9f1,0xac072c87,0xafed2e99,0x1fd91648,0x2fd4afbc,0xa9f12b05,0xad962f91,0x26a1a44e,0x2aaaae3f,0xa76528d5,0x251528d5,0x2993a875,
0x2fe6aeb5,0x2ddcadba,0xafff2f6e,0x2ed0aeb5,0x2e3fafbc,0x2e1fadfe,0xad272f30,0x2f02aee9,0x1fd9ab5e,0x2e5eae3f,0x244e2875,0x2f30af1a,0xad962993,0x2e99ae7c,0x2e99ac32,0x2f5aaf46,
0x299329f1,0xa76525db,0x251525db,0x2aaa1648,0x28d52934,0xaf02acd8,0x230e244e,0x2fa02dfe,0x28142875,0xaf91aff8,0x1fd9217e,0x2ee92ff4,0x26a12765,0xaa4eaddc,0x16481cb6,0x26a12cb0,
0x2f022f46,0x2b5e2e7c,0x2b5e2c32,0x230ea993,0x2e5e2eb5,0xab051648,0x29342a4e,0x2ee92c5d,0x2d962dfe,0xafddae5e,0x25db2814,0x2f5a2ffc,0x2cb02d27,0xaddcafaf,0x1cb6230e,0x27652d27,
0x2fd42f91,0x2f6e2fed,0x2dba2e5e,0xa6a1ad4d,0x2fff2ff8,0x25152d00,0x2c322d00,0x2ddc28d5,0x2faf2fe6,0xae1fa993,0x28d52aaa,0x2faf2fc9,0x2ee92f5a,0xaf91afdd,0x1fd925db,0x28142d96,
0x2cd82b5e,0x2f912d00,0x2f302faf,0xac07af1a,0x2eb52ddc,0x2d962fc9,0x2d962e7c,0x2c871cb6,0x2fc92f5a,0xa99326a1,0x2aaa2c87,0x2fe62f5a,0x2ff42ffc,0xaff8ae5e,0x217e2814,0x28752dfe,
0x9fd9a875,0x2c07a17e,0x2fed2ff8,0xadfeaff4,0x29f12515,0x2fdd2f46,0x2eb52f80,0x29f1a765,0x2ddc2c87,0x25152d96,0x2c322d96,0x2fff2eb5,0x2fa02ee9,0xaf02ab05,0x230e2934,0x28d52e5e,
0xad96aee9,0xa5dbadfe,0x2fdd2f30,0xaf5aafbc,0xa765abb7,0x2f462b5e,0x2f802ff8,0x2515abb7,0x28d51cb6,0x2d002fc9,0x2d002e7c,0x2ff82ddc,0x2dfe2c5d,0xacd81648,0x244e2a4e,0x29342eb5,
0xaff8afc9,0xae3fafff,0x2f022d72,0xaff8ae7c,0xadfeaf5a,0x2c07a5db,0x2fed2fdd,0x9fd9ad96,0xa6a1ac07,0x2f6e2f91,0x2dba2f30,0x2fd42cd8,0x2aaa230e,0xa7652b5e,0x25152b5e,0x29932f02,
0xae7cac5d,0xafffad96,0x2d7229f1,0xafc9ac5d,0xaff4afbc,0xa17eadfe,0x2ff82f30,0xa875aee9,0xad4daf1a,0x2fed2d00,0x2e5e2faf,0x2f912b5e,0x1648a993,0x25db2e7c,0x25db2c32,0x29f12f46,
0xaddc9648,0xafe6a6a1,0xaed0a6a1,0x2fff2a4e,0xad27affc,0x2d00ac07,0xabb7afbc,0xae1f2934,0x2e5e230e,0x1fd92fa0,0x2f3028d5,0x244eaf02,0x2c872fe6,0xadbaaf46,0x2a4e2f80,0x2c872fc9,
0xa30e2d72,0xad272c32,0xad272515,0x2faf1cb6,0xafbcae99,0x1fd9af6e,0xad4db000,0xacd82c87,0x2a4eab05,0x2c5d2fbc,0x2eb5244e,0x1648af91,0x2ed02fa0,0xaf80ad00,0x2aaa2faf,0x2cb02fa0,
0x2c872ffc,0x16482fbc,0xa9f12c07,0x2e99a934,0xaf80a8d5,0xac32afaf,0xae7cafaf,0xaaaa2e1f,0xa30eaed0,0x2f1a2d72,0x2e1f9cb6,0xa30eafe6,0x2fed2dba,0xaffca6a1,0x2b052fd4,0x2cd82f6e,
0x2fbc2e1f,0x2d4d2f02,0x9fd92e3f,0x2cd8ad27,0xac872993,0xaf5aacb0,0xaf5aaed0,0xa6a12f46,0xacb0b000,0x2fff25db,0x2d72a6a1,0xa765b000,0x2faf2934,0xaf1a2814,0x2b5e2fed,0x2d002f30,
0x2f30230e,0x2fed28d5,0x28142fa0,0x2934af02,0x16482ed0,0xafd41cb6,0xafddad72,0x16482fe6,0xaf46aeb5,0x2ed0a9f1,0x2cb0a9f1,0xa993afdd,0x2e1fa44e,0xad002d4d,0x2bb72ffc,0x2d272ee9,
0x2a4eacd8,0x2eb5ab05,0x2c5d2ffc,0x1648afed,0x2cb02ff4,0xad722d27,0xafffab5e,0x27652ff4,0xaff8aaaa,0x2bb7ae7c,0x2bb7ac32,0xab5eaf80,0x2b05ac87,0xa8142f6e,0x2c073000,0x2d4d2e99,
0xa8d5afe6,0x2875af80,0x2e3f2f46,0xa8d5afc9,0x2f912dba,0xa44e2fd4,0xafbca6a1,0x2b052f6e,0xae99244e,0x9648affc,0x29f1ad4d,0xac87aee9,0x1cb6af02,0x25152ff8,0x2c322ff8,0x2d722e3f,
0xaed0ae99,0xaaaaaf5a,0x2f802d96,0xacb0ae99,0x2faf244e,0x2b5e2f30,0xaf1a1fd9,0x2d002e5e,0xab052d27,0xac07af02,0x2814ae3f,0xad4dae1f,0xa9f1afff,0x2c5d2ed0,0x2c5d2fe6,0x2d962ddc,
0xaf46aa4e,0xac32ac87,0xae7cac87,0x29932dba,0x2f1a2b05,0xa8752fed,0x2e3f2cd8,0x2b5eaffc,0xaee9abb7,0x2f30ae1f,0xadfead27,0xafbc2d00,0x2eb52c32,0xaf6e1cb6,0x2dba2d72,0x2eb52515,
0xafaf2993,0xafa02515,0xafa0a765,0x2d002aaa,0x2feda6a1,0x29342d96,0x2f3029f1,0x2814afd4,0xb0001fd9,0x2c87afed,0xae99ac07,0xaf6e2dfe,0x2fe6217e,0xafff2bb7,0x2ddc2d00,0x2ed0217e,
0xac5d2f30,0xaf5a2e5e,0xb000244e,0x2eb51fd9,0x2ddcae1f,0x2e7c230e,0x2fc9230e,0x1cb6af1a,0xaf022cb0,0x217eaf46,0xaf1aa993,0xaf022ed0,0x2fbca9f1,0xaf302e99,0x2dfe2c87,0x2ee91648,
0x244e2fa0,0xab052ff4,0xaf912bb7,0x2fbca8d5,0x26a1afff,0x3000ac32,0x3000a515,0xa5dbaddc,0xac322f6e,0xaaaaac5d,0xaf80a5db,0xae7c2f6e,0x2e3fadfe,0xad272fed,0x2e1f2c07,0x2f029fd9,
0x2dfe2bb7,0x28142d27,0xae5e2e1f,0x2ffcad00,0xaa4eae7c,0x2e99af80,0x2fd4aaaa,0xaa4eac32,0x9cb62fdd,0xae7c9648,0xafc99648,0xaddc2fd4,0x2b5eafbc,0xa8752f91,0x2e3f2b05,0x2f1aa44e,
0x3000a814,0x2e999fd9,0xac872f91,0x2f6eaee9,0xaed0a875,0x2993afa0,0x2f46ad27,0xacb0a875,0x2b5e2ddc,0xaff42c32,0xaff42515,0xad272fff,0x1fd9afd4,0x244e2d96,0x2e5e29f1,0x2f30a6a1,
0x2e1faed0,0x2ff4addc,0xa8752fff,0x2e1fafe6,0xaffc29f1,0xa814ac87,0x2e5eae99,0xadfe9648,0x2eb52814,0xaf5a2f30,0xb0002934,0xac5d2fed,0xa993ae3f,0x2c3228d5,0x2e7c28d5,0x2f46a875,
0x2515afd4,0x2d72b000,0x1cb62f5a,0x2c32afd4,0xae3f2ee9,0xae1f1fd9,0x2d27af91,0xaf022814,0x2ffca8d5,0xacd82ff4,0xafed2bb7,0xab052fa0,0xad96aaaa,0x2e99a515,0x2e992765,0x2f5aa993,
0x1cb6adba,0x2cb0aeb5,0x2765aeb5,0xaddc2f6e,0xaff82d4d,0xa30ea814,0xafaf2c07,0xa17e2b05,0xa44e2e3f,0xadfe2b5e,0xa9342f1a,0x2cd8a875,0x2fddacb0,0xb0002f80,0x2f6eaaaa,0x2fddaed0,
0xad009cb6,0xa17ea765,0xa17eacb0,0xabb72ddc,0xaee92fdd,0xad4d2a4e,0xaffc2dba,0x244e25db,0x29f12934,0xafd42ee9,0xa6a12e5e,0x2d96ab05,0x2fc9af1a,0xaf462ff4,0x2f80abb7,0x2fe6af1a,
0xafdd2d4d,0xadba2c07,0xaa4ea814,0xa5db2b05,0xaaaa2f1a,0xafc92f02,0xafe62f02,0x2993a17e,0x2e3fa765,0xafa02fff,0xa17e2d72,0x2e3facb0,0x2e5eb000,0xad4d2eb5,0x2f91ac5d,0x2fedaf5a,
0xaee92ff8,0xaffc2faf,0xad4d230e,0x244e217e,0x25db2aaa,0xaf6e2fe6,0xaf6e2fc9,0x2c5da993,0x2fe6adba,0xad722e99,0x1cb62c5d,0x2ed0adba,0x2bb7af30,0xa8d52c07,0x2fa0acd8,0x2ff4af91,
0xa9342e3f,0xae5e2f1a,0xaee92b5e,0x2b05a875,0x2dbaa765,0xac5d2d72,0xae992fff,0x2dbaacb0,0x2f80afd4,0xa7652a4e,0x25152a4e,0x2f46ae99,0x217eacd8,0x230e1fd9,0x2fafad4d,0x2ff8afbc,
0x29f1244e,0xa6a12934,0xafd42dfe,0x2d96acd8,0x2fe6ae3f,0x1cb6217e,0xad722fa0,0x2ed0ae3f,0x2d27af80,0x2875a515,0x28752765,0x2fa0af46,0xa934a5db,0x2c07aa4e,0x2fbcadba,0x2ffcafdd,
0x2f1aacb0,0x2bb7aaaa,0xaff42f80,0x2f1aaed0,0x2f30b000,0x2cd8ac5d,0xac072eb5,0x2f91af5a,0x25dbacd8,0x2dbaad4d,0x2a4e1fd9,0x2fddafbc,0xad722875,0x2e7cae1f,0x2fc9ae1f,0x2fffaff4,
0x2fc9afdd,0x2f80af6e,0xaf463000,0x2fe6afdd,0x2bb7ae5e,0x2fa0af91,0xa8d52d4d,0x2ff4afed,0xa934a17e,0x2fbcafaf,0x2c07a30e,0x2ffcaff8,0xaf5a2d72,0x2fd4afc9,0x2fd4ae7c,0x3000afff,
0x9d4d9e16,0xada6ae7d,0x9b769c84,0xabf0accf,0x985299e4,0xa897aa43,0x90b6957f,0xa102a5d8,0x13db0a48,0x242c1aad,0x191b1712,0x296d2783,0x1c201aad,0x2c632b1a,0x1db21ce9,0x2e112d3a,
0xa3f4a491,0xae51af42,0xa199a2c6,0xac70ad60,0x9e7ba06b,0xa922ab00,0x97129c20,0xa199a688,0x19e410b6,0x24aa1b76,0x1fa81d4d,0x2a112833,0x222f2102,0x2ce82bf0,0x2445235d,0x2ec92dd8,
0xa6a1a79c,0xaefcb004,0xa4aaa5a5,0xace8adf2,0xa166a35d,0xa9acabbe,0x99e49edf,0xa22fa738,0x1ce913db,0x25281c20,0x2262206b,0x2ab528a4,0x2528242c,0x2d6d2c63,0x271f2623,0x2f822e77,
0xa8a4a954,0xafa8b067,0xa688a7e8,0xad60ae84,0xa38fa528,0xaa37ac3d,0x9c20a0d0,0xa2c6a7e8,0x1edf157f,0x25a51c84,0x2478222f,0x2b592915,0x273825d8,0x2df22ccf,0x28fc284c,0x301d2f16,
0xa9f8aadb,0xb02ab0ca,0xa833a915,0xadd8af16,0xa4dca6a1,0xaac1ac9c,0x9d4da22f,0xa35da84c,0x206b1712,0x26231ce9,0x25bf23f4,0x2bfd2987,0x28a42783,0x2e772d3a,0x2a692987,0x307a2fb5,
0xab4cac31,0xb081b12e,0xa922aa37,0xae51afa8,0xa5f1a80d,0xab4cacfb,0x9e7ba38f,0xa3f4a8a4,0x21661852,0x26a11d4d,0x270524dc,0x2c5029f8,0x29ac2897,0x2efc2da6,0x2bd72ac1,0x30d7302a,
0xac50acf5,0xb0d7b192,0xaa11ab59,0xaec9b01d,0xa705a8ca,0xabd7ad5a,0x9fa8a478,0xa445a8fc,0x2262191b,0x271f1db2,0x282625bf,0x2ca22a69,0x2ab5296d,0x2f822e11,0x2ca22bfd,0x3135307a,
0xacfbadb9,0xb12eb1f7,0xab00ac3d,0xaf42b067,0xa80da987,0xac31adb9,0xa06ba528,0xa491a954,0x235d19e4,0x279c1e16,0x28ca26a1,0x2cf52adb,0x2bbe2a43,0x30042e7d,0x2d5a2c9c,0x319230ca,
0xb185b25c,0xb426b4cc,0xafbbb0b1,0xb1c6b306,0xac76ae18,0xaea3b08a,0xa4dca9ac,0xa738ac37,0x280d1e7b,0x2a0520d0,0x2d472b4c,0x2fdb2d6d,0x30472ee9,0x32663128,0x31f0311b,0x347933a8,
0xb1ddb2c1,0xb453b501,0xb01ab0fb,0xb204b352,0xacbcae77,0xaee9b0ba,0xa528aa05,0xa783ac63,0x284c1edf,0x2a432102,0x2d992bbe,0x30172da6,0x308a2f55,0x32aa315f,0x324f316b,0x34aa33fc,
0xb235b327,0xb481b537,0xb057b145,0xb242b39e,0xad01aed6,0xaf2fb0eb,0xa573aa5d,0xa7cfac90,0x288b1f44,0x2a822134,0x2deb2c18,0x30412ddf,0x30ce2fc2,0x32ef3196,0x32ae31bc,0x34db3428,
0xb28db38e,0xb4afb56d,0xb094b18f,0xb280b3eb,0xad47af36,0xaf75b11b,0xa5bfaab5,0xa80dacbc,0x28ca1fa8,0x2ac12166,0x2e3e2c50,0x306a2e18,0x31113017,0x333531cd,0x330d320e,0x350d3452,
0xb2e5b3f5,0xb4ddb5a3,0xb0d1b1da,0xb2beb41c,0xad8caf95,0xafbbb14b,0xa60aab0d,0xa833ace8,0x29092006,0x2b002199,0x2e902c89,0x30942e51,0x3155304d,0x337a3204,0x336d325f,0x3540347c,
0xb33eb42e,0xb50cb5da,0xb10eb224,0xb2fcb443,0xadd2aff5,0xb001b17c,0xa655ab65,0xa859ad14,0x29482039,0x2b4021cb,0x2ee32cc2,0x30be2e8a,0x31993084,0x33c0323b,0x33cd32b1,0x357234a6,
0xb398b463,0xb53ab612,0xb14bb26f,0xb33bb469,0xae18b02a,0xb024b1ac,0xa6a1abbe,0xa87ead40,0x2987206b,0x2b7f21fd,0x2f362cfb,0x30e72ec3,0x31dd30ba,0x34033273,0x34173303,0x35a534d1,
0xb3f2b497,0xb569b64a,0xb189b2bb,0xb37ab490,0xae5eb05a,0xb047b1dd,0xa6ecac0b,0xa8a4ad6d,0x29c6209d,0x2bbe222f,0x2f882d34,0x31112efc,0x322130f1,0x342632aa,0x34483356,0x35d934fc,
0xb599b682,0xb722b82e,0xb3b9b4b7,0xb4ddb5f9,0xb06ab20e,0xb185b398,0xa8caad99,0xa9f8aefc,0x2bfd2262,0x2cfb23f4,0x313b2f36,0x328d3081,0x344932e2,0x35693453,0x360d3527,0x37bd368b,
0xb5c9b6bb,0xb755b84d,0xb3f8b4df,0xb4feb622,0xb08db23e,0xb1a9b3ca,0xa8f0adc5,0xaa1eaf29,0x2c1e2294,0x2d1b2413,0x31652f6f,0x32b7309d,0x346d331a,0x358e3470,0x36413553,0x37f536ba,
0xb5f9b6f5,0xb789b86d,0xb41cb506,0xb51fb64c,0xb0b1b26f,0xb1cdb3fc,0xa915adf2,0xaa43af55,0x2c3d22c6,0x2d3a242c,0x318f2fa8,0x32e230ba,0x34903352,0x35b3348d,0x3676357e,0x381736e8,
0xb629b72f,0xb7bdb88d,0xb43cb52e,0xb540b676,0xb0d4b2a1,0xb1f0b417,0xa93bae1e,0xaa69af82,0x2c5d22f9,0x2d5a2445,0x31b92fe2,0x330d30d7,0x34b4338b,0x35d934aa,0x36ab35ab,0x38343717,
0xb65ab76a,0xb7f1b8ad,0xb45cb556,0xb561b6a0,0xb0f7b2d2,0xb214b430,0xa961ae4b,0xaa8fafaf,0x2c7d232b,0x2d79245f,0x31e3300e,0x333830f4,0x34d833c3,0x35fe34c7,0x36e035d7,0x38513746,
0xb68bb7a5,0xb813b8ce,0xb47cb57e,0xb582b6ca,0xb11bb303,0xb238b449,0xa987ae77,0xaab5afdb,0x2c9c235d,0x2d992478,0x320e302a,0x33633111,0x34fc33fc,0x362434e4,0x37173604,0x386f3775,
0xb6bdb7e2,0xb82eb8f0,0xb49cb5a7,0xb5a3b6f5,0xb13eb335,0xb25cb463,0xa9acaea3,0xaadbb004,0x2cbc238f,0x2db92491,0x32383047,0x338e312e,0x3520341a,0x364a3501,0x374d3631,0x388d37a5,
0xb6efb80f,0xb849b911,0xb4bdb5d0,0xb5c5b720,0xb162b366,0xb280b47c,0xa9d2aed0,0xab00b01a,0x2cdb23c2,0x2dd824aa,0x32623064,0x33b9314b,0x35453437,0x3670351f,0x3785365e,0x38ab37d6,
0xb865b934,0xb94dba5c,0xb5e7b74c,0xb6fcb85a,0xb2a4b495,0xb3c6b564,0xab26b031,0xac2bb0e4,0x2df824c3,0x2ef6258c,0x33e43168,0x34a13252,0x3697353c,0x37d4362d,0x38ca3803,0x39d038d0,
0xb880b957,0xb96bba84,0xb609b777,0xb720b872,0xb2c8b4af,0xb3ebb57e,0xab4cb047,0xac3db0fb,0x2e1824dc,0x2f1625a5,0x34083185,0x34b7326f,0x36bd355a,0x37fd364c,0x38e9381c,0x39f338eb,
0xb89cb97a,0xb98abaad,0xb62bb7a4,0xb744b88a,0xb2ecb4c9,0xb408b599,0xab72b05d,0xac50b111,0x2e3724f5,0x2f3625bf,0x341e31a2,0x34ce328d,0x36e43577,0x3813366b,0x39093835,0x3a173906,
0xb8b9b99e,0xb9aabad7,0xb64db7d0,0xb768b8a2,0xb310b4e2,0xb41ab5b3,0xab98b074,0xac63b128,0x2e57250f,0x2f5525d8,0x343331c0,0x34e432aa,0x370b3595,0x3828368a,0x3929384e,0x3a3b3922,
0xb8d6b9c3,0xb9cabb02,0xb670b7fd,0xb78cb8ba,0xb335b4fc,0xb42db5ce,0xabbeb08a,0xac76b13e,0x2e772528,0x2f7525f1,0x344931dd,0x34fa32c8,0x373335b3,0x383d36a9,0x39493868,0x3a60393e,
0xb8f3b9e8,0xb9ebbb2d,0xb693b815,0xb7b1b8d2,0xb359b516,0xb43fb5e9,0xabe3b0a1,0xac89b155,0x2e972541,0x2f95260a,0x345f31fa,0x351132e5,0x375b35d2,0x385236c8,0x396a3881,0x3a86395a,
0xb910ba0e,0xba0cbb59,0xb6b6b82c,0xb7d6b8eb,0xb37db530,0xb452b604,0xac05b0b7,0xac9cb16b,0x2eb6255a,0x2fb52623,0x34753217,0x35273303,0x378335f0,0x386836e8,0x398c389b,0x3aac3977,
0xb92eba35,0xba2dbb87,0xb6d9b843,0xb7fbb904,0xb3a2b54a,0xb464b61e,0xac18b0ce,0xacafb182,0x2ed62573,0x2fd5263c,0x348b3235,0x353e3321,0x37ab360e,0x387d3708,0x39ae38b6,0x3ad33994,
0x9ce99db2,0xad3aae11,0x9aad9c20,0xab1aac63,0x9712991b,0xa783a96d,0x8a4893db,0x9aada42c,0x157f10b6,0x25d82102,0x19e41852,0x2a432897,0x1c841b76,0x2ccf2bf0,0x1e161d4d,0x2e7d2da6,
0xa35da445,0xadd8aec9,0xa102a22f,0xabf0ace8,0x9d4d9fa8,0xa833aa11,0x90b699e4,0x9b76a4aa,0x1c201712,0x26882199,0x206b1e7b,0x2b002922,0x22c62199,0x2d602c70,0x249123f4,0x2f422e51,
0xa623a71f,0xae77af82,0xa42ca528,0xac63ad6d,0xa06ba262,0xa8a4aab5,0x93db9ce9,0x9c20a528,0x1edf19e4,0x2738222f,0x235d2166,0x2bbe29ac,0x25a524aa,0x2df22ce8,0x279c26a1,0x30042efc,
0xa84ca8fc,0xaf16b01d,0xa5d8a738,0xaccfadf2,0xa22fa478,0xa915ab59,0x957f9edf,0x9c84a5a5,0x20d01c20,0x27e822c6,0x2528238f,0x2c3d2a37,0x27e82688,0x2e842d60,0x295428a4,0x30672fa8,
0xa987aa69,0xafb5b07a,0xa783a8a4,0xad3aae77,0xa3f4a5bf,0xa987abfd,0x9712a06b,0x9ce9a623,0x222f1d4d,0x284c235d,0x26a124dc,0x2c9c2ac1,0x29152833,0x2f162dd8,0x2adb29f8,0x30ca302a,
0xaac1abd7,0xb02ab0d7,0xa897a9ac,0xada6aefc,0xa4dca705,0xa9f8ac50,0x9852a166,0x9d4da6a1,0x238f1e7b,0x28a423f4,0x280d25f1,0x2cfb2b4c,0x2a372922,0x2fa82e51,0x2c312b4c,0x312e3081,
0xabfdaca2,0xb07ab135,0xa96daab5,0xae11af82,0xa5bfa826,0xaa69aca2,0x991ba262,0x9db2a71f,0x24781fa8,0x28fc2445,0x28ca2705,0x2d5a2bd7,0x2b592a11,0x301d2ec9,0x2cf52c50,0x319230d7,
0xac9cad5a,0xb0cab192,0xaa43abbe,0xae7db004,0xa6a1a8ca,0xaadbacf5,0x99e4a35d,0x9e16a79c,0x2528206b,0x29542491,0x2987280d,0x2db92c31,0x2c3d2b00,0x30672f42,0x2db92cfb,0x31f7312e,
0xb11bb1f0,0xb3a8b479,0xaee9b047,0xb128b266,0xab4cad47,0xad6dafdb,0x9e7ba80d,0xa0d0aa05,0x29ac24dc,0x2c372738,0x2e182c76,0x308a2ea3,0x30b12fbb,0x330631c6,0x325c3185,0x34cc3426,
0xb16bb24f,0xb3fcb4aa,0xaf55b08a,0xb15fb2aa,0xabbead99,0xada6b017,0x9edfa84c,0xa102aa43,0x2a052528,0x2c632783,0x2e772cbc,0x30ba2ee9,0x30fb301a,0x33523204,0x32c131dd,0x35013453,
0xb1bcb2ae,0xb428b4db,0xafc2b0ce,0xb196b2ef,0xac18adeb,0xaddfb041,0x9f44a88b,0xa134aa82,0x2a5d2573,0x2c9027cf,0x2ed62d01,0x30eb2f2f,0x31453057,0x339e3242,0x33273235,0x35373481,
0xb20eb30d,0xb452b50d,0xb017b111,0xb1cdb335,0xac50ae3e,0xae18b06a,0x9fa8a8ca,0xa166aac1,0x2ab525bf,0x2cbc280d,0x2f362d47,0x311b2f75,0x318f3094,0x33eb3280,0x338e328d,0x356d34af,
0xb25fb36d,0xb47cb540,0xb04db155,0xb204b37a,0xac89ae90,0xae51b094,0xa006a909,0xa199ab00,0x2b0d260a,0x2ce82833,0x2f952d8c,0x314b2fbb,0x31da30d1,0x341c32be,0x33f532e5,0x35a334dd,
0xb2b1b3cd,0xb4a6b572,0xb084b199,0xb23bb3c0,0xacc2aee3,0xae8ab0be,0xa039a948,0xa1cbab40,0x2b652655,0x2d142859,0x2ff52dd2,0x317c3001,0x3224310e,0x344332fc,0x342e333e,0x35da350c,
0xb303b417,0xb4d1b5a5,0xb0bab1dd,0xb273b403,0xacfbaf36,0xaec3b0e7,0xa06ba987,0xa1fdab7f,0x2bbe26a1,0x2d40287e,0x302a2e18,0x31ac3024,0x326f314b,0x3469333b,0x34633398,0x3612353a,
0xb356b448,0xb4fcb5d9,0xb0f1b221,0xb2aab426,0xad34af88,0xaefcb111,0xa09da9c6,0xa22fabbe,0x2c0b26ec,0x2d6d28a4,0x305a2e5e,0x31dd3047,0x32bb3189,0x3490337a,0x349733f2,0x364a3569,
0xb527b60d,0xb68bb7bd,0xb2e2b449,0xb453b569,0xaf36b13b,0xb081b28d,0xa262abfd,0xa3f4acfb,0x2d9928ca,0x2efc29f8,0x320e306a,0x33983185,0x34b733b9,0x35f934dd,0x36823599,0x382e3722,
0xb553b641,0xb6bab7f5,0xb31ab46d,0xb470b58e,0xaf6fb165,0xb09db2b7,0xa294ac1e,0xa413ad1b,0x2dc528f0,0x2f292a1e,0x323e308d,0x33ca31a9,0x34df33f8,0x362234fe,0x36bb35c9,0x384d3755,
0xb57eb676,0xb6e8b817,0xb352b490,0xb48db5b3,0xafa8b18f,0xb0bab2e2,0xa2c6ac3d,0xa42cad3a,0x2df22915,0x2f552a43,0x326f30b1,0x33fc31cd,0x3506341c,0x364c351f,0x36f535f9,0x386d3789,
0xb5abb6ab,0xb717b834,0xb38bb4b4,0xb4aab5d9,0xafe2b1b9,0xb0d7b30d,0xa2f9ac5d,0xa445ad5a,0x2e1e293b,0x2f822a69,0x32a130d4,0x341731f0,0x352e343c,0x36763540,0x372f3629,0x388d37bd,
0xb5d7b6e0,0xb746b851,0xb3c3b4d8,0xb4c7b5fe,0xb00eb1e3,0xb0f4b338,0xa32bac7d,0xa45fad79,0x2e4b2961,0x2faf2a8f,0x32d230f7,0x34303214,0x3556345c,0x36a03561,0x376a365a,0x38ad37f1,
0xb604b717,0xb775b86f,0xb3fcb4fc,0xb4e4b624,0xb02ab20e,0xb111b363,0xa35dac9c,0xa478ad99,0x2e772987,0x2fdb2ab5,0x3303311b,0x34493238,0x357e347c,0x36ca3582,0x37a5368b,0x38ce3813,
0xb631b74d,0xb7a5b88d,0xb41ab520,0xb501b64a,0xb047b238,0xb12eb38e,0xa38facbc,0xa491adb9,0x2ea329ac,0x30042adb,0x3335313e,0x3463325c,0x35a7349c,0x36f535a3,0x37e236bd,0x38f0382e,
0xb65eb785,0xb7d6b8ab,0xb437b545,0xb51fb670,0xb064b262,0xb14bb3b9,0xa3c2acdb,0xa4aaadd8,0x2ed029d2,0x301a2b00,0x33663162,0x347c3280,0x35d034bd,0x372035c5,0x380f36ef,0x39113849,
0xb803b8ca,0xb8d0b9d0,0xb53cb697,0xb62db7d4,0xb168b3e4,0xb252b4a1,0xa4c3adf8,0xa58caef6,0x30312b26,0x30e42c2b,0x349532a4,0x356433c6,0x374c35e7,0x385a36fc,0x39343865,0x3a5c394d,
0xb81cb8e9,0xb8ebb9f3,0xb55ab6bd,0xb64cb7fd,0xb185b408,0xb26fb4b7,0xa4dcae18,0xa5a5af16,0x30472b4c,0x30fb2c3d,0x34af32c8,0x357e33eb,0x37773609,0x38723720,0x39573880,0x3a84396b,
0xb835b909,0xb906ba17,0xb577b6e4,0xb66bb813,0xb1a2b41e,0xb28db4ce,0xa4f5ae37,0xa5bfaf36,0x305d2b72,0x31112c50,0x34c932ec,0x35993408,0x37a4362b,0x388a3744,0x397a389c,0x3aad398a,
0xb84eb929,0xb922ba3b,0xb595b70b,0xb68ab828,0xb1c0b433,0xb2aab4e4,0xa50fae57,0xa5d8af55,0x30742b98,0x31282c63,0x34e23310,0x35b3341a,0x37d0364d,0x38a23768,0x399e38b9,0x3ad739aa,
0xb868b949,0xb93eba60,0xb5b3b733,0xb6a9b83d,0xb1ddb449,0xb2c8b4fa,0xa528ae77,0xa5f1af75,0x308a2bbe,0x313e2c76,0x34fc3335,0x35ce342d,0x37fd3670,0x38ba378c,0x39c338d6,0x3b0239ca,
0xb881b96a,0xb95aba86,0xb5d2b75b,0xb6c8b852,0xb1fab45f,0xb2e5b511,0xa541ae97,0xa60aaf95,0x30a12be3,0x31552c89,0x35163359,0x35e9343f,0x38153693,0x38d237b1,0x39e838f3,0x3b2d39eb,
0xb89bb98c,0xb977baac,0xb5f0b783,0xb6e8b868,0xb217b475,0xb303b527,0xa55aaeb6,0xa623afb5,0x30b72c05,0x316b2c9c,0x3530337d,0x36043452,0x382c36b6,0x38eb37d6,0x3a0e3910,0x3b593a0c,
0xb8b6b9ae,0xb994bad3,0xb60eb7ab,0xb708b87d,0xb235b48b,0xb321b53e,0xa573aed6,0xa63cafd5,0x30ce2c18,0x31822caf,0x354a33a2,0x361e3464,0x384336d9,0x390437fb,0x3a35392e,0x3b873a2d,
0x214d2216,0x319b326c,0x1f762084,0x2fe830c8,0x1c521de4,0x2c962e40,0x14b6197f,0x250229d7,0x97db8e48,0xa82c9ead,0x9d1b9b12,0xad6bab82,0xa0209ead,0xb05eaf14,0xa1b2a0e9,0xb204b131,
0x27f32890,0x3241332b,0x259826c6,0x306a3156,0x227b246b,0x2d202efb,0x1b122020,0x25982a87,0x9de494b6,0xa8aa9f76,0xa3a8a14d,0xae0eac32,0xa62fa502,0xb0e1afe8,0xa845a75d,0xb2b6b1cc,
0x2aa02b9b,0x32e733e8,0x28aa29a5,0x30e131e5,0x2566275d,0x2daa2fb6,0x1de422df,0x262f2b36,0xa0e997db,0xa927a020,0xa661a46b,0xaeb0aca2,0xa927a82c,0xb163b05e,0xab1daa22,0xb368b266,
0x2ca22d52,0x338d3452,0x2a872be6,0x31563273,0x278f2927,0x2e333039,0x202024cf,0x26c62be6,0xa2df997f,0xa9a5a084,0xa877a62f,0xaf53ad13,0xab36a9d7,0xb1e5b0c8,0xacfaac4b,0xb40cb300,
0x2df52ed6,0x341834b0,0x2c322d13,0x31cc3300,0x28dc2aa0,0x2ebd3096,0x214d262f,0x275d2c4b,0xa46b9b12,0xaa22a0e9,0xa9bea7f3,0xaff5ad84,0xaca2ab82,0xb266b131,0xae65ad84,0xb464b399,
0x2f46302c,0x346a350c,0x2d202e33,0x3241338d,0x29f02c0c,0x2f4630f3,0x227b278f,0x27f32ca2,0xa5669c52,0xaaa0a14d,0xab04a8dc,0xb04badf5,0xadaaac96,0xb2e7b19b,0xafcfaebd,0xb4bcb418,
0x304b30ed,0x34bc3568,0x2e0e2f53,0x32b6340c,0x2b042cc8,0x2fcf3150,0x23a82877,0x28452cfa,0xa6619d1b,0xab1da1b2,0xac25a9be,0xb09cae65,0xaeb0ad6b,0xb368b204,0xb09caff5,0xb512b464,
0x30f331ad,0x350c35c4,0x2efb3039,0x332b3452,0x2c0c2d84,0x302c31ad,0x246b2927,0x28902d52,0xa75d9de4,0xab9ba216,0xacc8aaa0,0xb0edaed6,0xafb6ae40,0xb3e8b26c,0xb150b096,0xb568b4b0,
0x355d361e,0x37c63867,0x339f3497,0x359836b4,0x3071320a,0x32913473,0x28dc2daa,0x2b363032,0xac0ca27b,0xae01a4cf,0xb13eaf46,0xb3bdb163,0xb434b2d5,0xb627b506,0xb5beb4fa,0xb826b73e,
0x35ac3678,0x3808388f,0x340934dd,0x35cf36f5,0x30b53266,0x32d534a0,0x29272e01,0x2b82305e,0xac4ba2df,0xae40a502,0xb18eafb6,0xb406b19b,0xb473b33d,0xb663b539,0xb612b545,0xb84cb784,
0x35fb36d0,0x382c38b7,0x34433521,0x36073736,0x30f932c2,0x331834ce,0x29722e59,0x2bcd308a,0xac89a344,0xae7ea534,0xb1dfb013,0xb42eb1d2,0xb4b3b3a5,0xb6a0b56b,0xb666b58f,0xb872b7c9,
0x36493728,0x385038de,0x347c3565,0x363e3776,0x313e331e,0x335c34fa,0x29be2eb0,0x2c0c30b5,0xacc8a3a8,0xaebda566,0xb22fb04b,0xb455b20a,0xb4f1b406,0xb6dcb59d,0xb6b9b5d8,0xb898b807,
0x3697377e,0x38743904,0x34b635a9,0x367537b6,0x3182337a,0x339f3527,0x2a092f08,0x2c3230e1,0xad07a406,0xaefba598,0xb27fb083,0xb47cb241,0xb530b43a,0xb717b5cf,0xb70cb621,0xb8bdb828,
0x36e437d4,0x3897392a,0x34ee35ed,0x36ab37f5,0x31c633d6,0x33e23554,0x2a542f5f,0x2c57310c,0xad45a439,0xaf3aa5cb,0xb2cfb0bb,0xb4a4b279,0xb56eb46d,0xb752b601,0xb75db669,0xb8e1b84a,
0x37303814,0x38b9394e,0x3527362f,0x36e1381a,0x320a3418,0x34123580,0x2aa02fb6,0x2c7d3137,0xad84a46b,0xaf78a5fd,0xb31eb0f3,0xb4cbb2b0,0xb5acb4a0,0xb78cb632,0xb7adb6b1,0xb905b86b,
0x377c383e,0x38db3972,0x355f3672,0x37173838,0x324e3446,0x343435ac,0x2aeb3007,0x2ca23163,0xadc3a49d,0xafb6a62f,0xb36eb12b,0xb4f1b2e7,0xb5eab4d4,0xb7c6b663,0xb7fdb6f8,0xb928b88b,
0x38fd3996,0x39f33a91,0x374c3857,0x3874393e,0x345535d8,0x355d3730,0x2cc8318e,0x2df532e7,0xaff5a661,0xb0f3a7f3,0xb518b31e,0xb649b46a,0xb800b694,0xb8dbb808,0xb94bb8ab,0xba45b99b,
0x391e39b8,0x3a0f3aad,0x37813875,0x388c3959,0x34763604,0x357d375a,0x2cee31b9,0x2e1a3312,0xb01aa694,0xb112a813,0xb53fb356,0xb66fb485,0xb81cb6c5,0xb8f5b81f,0xb96db8cb,0xba61b9b7,
0x393e39da,0x3a2b3ac7,0x37b63893,0x38a53974,0x3497362f,0x359d3784,0x2d1331e5,0x2e40333d,0xb039a6c6,0xb131a82c,0xb565b38d,0xb694b4a0,0xb838b6f5,0xb90fb836,0xb98eb8ea,0xba7cb9d2,
0x395e39fb,0x3a453ae0,0x37ea38b0,0x38bd398e,0x34b9365b,0x35be37ad,0x2d393210,0x2e653368,0xb058a6f8,0xb150a845,0xb58cb3c3,0xb6b9b4bc,0xb854b725,0xb928b84c,0xb9aeb909,0xba97b9ed,
0x397d3a1b,0x3a5f3af9,0x380f38cd,0x38d539a8,0x34da3686,0x35de37d7,0x2d5e323b,0x2e8b3393,0xb077a72a,0xb16fa85e,0xb5b2b3fa,0xb6deb4d7,0xb870b755,0xb941b863,0xb9ceb927,0xbab0ba07,
0x399b3a3a,0x3a793b10,0x382838ea,0x38ed39c1,0x34fa36b1,0x35fe3800,0x2d843266,0x2eb033bd,0xb096a75d,0xb18ea877,0xb5d8b418,0xb703b4f1,0xb88bb784,0xb95ab879,0xb9edb945,0xbac9ba21,
0x39b93a58,0x3a913b26,0x38423906,0x390439da,0x351b36dc,0x361e3814,0x2daa3291,0x2ed633e8,0xb0b5a78f,0xb1ada890,0xb5feb434,0xb728b50c,0xb8a6b7b3,0xb972b88f,0xba0bb962,0xbae0ba3a,
0x39d73a75,0x3aa93b3c,0x385b3922,0x391b39f2,0x353c3706,0x363e3828,0x2dcf32bc,0x2efb3409,0xb0d4a7c1,0xb1cca8aa,0xb624b44f,0xb74cb527,0xb8c1b7e2,0xb98ab8a5,0xba29b97f,0xbaf7ba52,
0x3ac03b50,0x3b5e3bcb,0x39323a0a,0x39de3ab8,0x365e383c,0x375738d7,0x2f21341f,0x302634c8,0xb1eba8c3,0xb2e1a98c,0xb770b542,0xb846b615,0xb9a2b8bb,0xba51b960,0xbb0dba6a,0xbb9cbb11,
0x3ad73b63,0x3b6e3bd6,0x39493a22,0x39f23acb,0x367d3850,0x377638ea,0x2f463434,0x303934dd,0xb20aa8dc,0xb300a9a5,0xb795b55d,0xb857b62f,0xb9b9b8d0,0xba65b974,0xbb22ba81,0xbba9bb24,
0x3aec3b75,0x3b7d3bdf,0x395f3a39,0x3a063ade,0x369d3864,0x379538fd,0x2f6c3449,0x304b34f1,0xb229a8f5,0xb31ea9be,0xb7b8b577,0xb868b649,0xb9d0b8e5,0xba79b987,0xbb36ba97,0xbbb6bb35,
0x3b013b86,0x3b8c3be7,0x39753a4f,0x3a193af0,0x36bc3878,0x37b3390f,0x2f91345e,0x305e3506,0xb247a90e,0xb33da9d7,0xb7dcb592,0xb879b663,0xb9e7b8fa,0xba8cb99a,0xbb4abaad,0xbbc2bb46,
0x3b153b96,0x3b993bee,0x398a3a65,0x3a2d3b02,0x36dc388b,0x37d13921,0x2fb63473,0x3071351b,0xb266a927,0xb35ca9f0,0xb800b5ac,0xb88ab67d,0xb9fdb90f,0xba9fb9ad,0xbb5cbac3,0xbbccbb56,
0x3b283ba5,0x3ba63bf4,0x39a03a7a,0x3a3f3b13,0x36fb389e,0x37ef3933,0x2fdc3488,0x30833530,0xb285a940,0xb37aaa09,0xb811b5c7,0xb89bb697,0xba12b924,0xbab1b9c0,0xbb6dbad7,0xbbd6bb65,
0x3b3b3bb3,0x3bb23bf9,0x39b53a8f,0x3a523b24,0x371a38b2,0x38073945,0x3001349d,0x30963545,0xb2a4a959,0xb399aa22,0xb823b5e1,0xb8abb6b1,0xba28b938,0xbac3b9d2,0xbb7ebaeb,0xbbdfbb74,
0x3b4d3bc0,0x3bbd3bfc,0x39ca3aa4,0x3a643b34,0x373938c5,0x38153957,0x301334b3,0x30a9355a,0xb2c2a972,0xb3b7aa3b,0xb834b5fb,0xb8bcb6ca,0xba3cb94c,0xbad4b9e4,0xbb8dbaff,0xbbe6bb82,
0x20e921b2,0x31313204,0x1ead2020,0x2f14305e,0x1b121d1b,0x2b822d6b,0xe4817db,0x1ead282c,0x997f94b6,0xa9d7a502,0x9de49c52,0xae40ac96,0xa0849f76,0xb0c8afe8,0xa216a14d,0xb26cb19b,
0x275d2845,0x31cc32b6,0x2502262f,0x2fe830e1,0x214d23a8,0x2c322e0e,0x14b61de4,0x1f7628aa,0xa0209b12,0xaa87a598,0xa46ba27b,0xaefbad20,0xa6c6a598,0xb156b06a,0xa890a7f3,0xb32bb241,
0x2a222b1d,0x32663368,0x282c2927,0x305e3163,0x246b2661,0x2ca22eb0,0x17db20e9,0x20202927,0xa2df9de4,0xab36a62f,0xa75da566,0xafb6adaa,0xa9a5a8aa,0xb1e5b0e1,0xab9baaa0,0xb3e8b2e7,
0x2c4b2cfa,0x3300340c,0x29d72b36,0x30c831e5,0x262f2877,0x2d132f53,0x197f22df,0x208429a5,0xa4cfa020,0xabe6a6c6,0xa927a78f,0xb039ae33,0xabe6aa87,0xb273b156,0xad52aca2,0xb452b38d,
0x2d842e65,0x33993464,0x2b822ca2,0x31313266,0x27f329be,0x2d842ff5,0x1b12246b,0x20e92a22,0xa62fa14d,0xac4ba75d,0xaaa0a8dc,0xb096aebd,0xad13ac32,0xb300b1cc,0xaed6adf5,0xb4b0b418,
0x2ebd2fcf,0x341834bc,0x2c962daa,0x319b32e7,0x28dc2b04,0x2df5304b,0x1c522566,0x214d2aa0,0xa78fa27b,0xaca2a7f3,0xac0ca9f0,0xb0f3af46,0xae33ad20,0xb38db241,0xb02caf46,0xb50cb46a,
0x2ff5309c,0x34643512,0x2d6b2eb0,0x32043368,0x29be2c25,0x2e65309c,0x1d1b2661,0x21b22b1d,0xa877a3a8,0xacfaa845,0xacc8ab04,0xb150afcf,0xaf53ae0e,0xb40cb2b6,0xb0edb04b,0xb568b4bc,
0x30963150,0x34b03568,0x2e402fb6,0x326c33e8,0x2aa02cc8,0x2ed630ed,0x1de4275d,0x22162b9b,0xa927a46b,0xad52a890,0xad84ac0c,0xb1adb02c,0xb039aefb,0xb452b32b,0xb1adb0f3,0xb5c4b50c,
0x34fa35be,0x373e3826,0x32d53434,0x35063627,0x2f46313e,0x316333bd,0x227b2c0c,0x24cf2e01,0xadaaa8dc,0xb032ab36,0xb20ab071,0xb473b291,0xb497b39f,0xb6b4b598,0xb61eb55d,0xb867b7c6,
0x35453612,0x3784384c,0x333d3473,0x35393663,0x2fb6318e,0x319b3406,0x22df2c4b,0x25022e40,0xae01a927,0xb05eab82,0xb266b0b5,0xb4a0b2d5,0xb4ddb409,0xb6f5b5cf,0xb678b5ac,0xb88fb808,
0x358f3666,0x37c93872,0x33a534b3,0x356b36a0,0x301331df,0x31d2342e,0x23442c89,0x25342e7e,0xae59a972,0xb08aabcd,0xb2c2b0f9,0xb4ceb318,0xb521b443,0xb736b607,0xb6d0b5fb,0xb8b7b82c,
0x35d836b9,0x38073898,0x340634f1,0x359d36dc,0x304b322f,0x320a3455,0x23a82cc8,0x25662ebd,0xaeb0a9be,0xb0b5ac0c,0xb31eb13e,0xb4fab35c,0xb565b47c,0xb776b63e,0xb728b649,0xb8deb850,
0x3621370c,0x382838bd,0x343a3530,0x35cf3717,0x3083327f,0x3241347c,0x24062d07,0x25982efb,0xaf08aa09,0xb0e1ac32,0xb37ab182,0xb527b39f,0xb5a9b4b6,0xb7b6b675,0xb77eb697,0xb904b874,
0x3669375d,0x384a38e1,0x346d356e,0x36013752,0x30bb32cf,0x327934a4,0x24392d45,0x25cb2f3a,0xaf5faa54,0xb10cac57,0xb3d6b1c6,0xb554b3e2,0xb5edb4ee,0xb7f5b6ab,0xb7d4b6e4,0xb92ab897,
0x36b137ad,0x386b3905,0x34a035ac,0x3632378c,0x30f3331e,0x32b034cb,0x246b2d84,0x25fd2f78,0xafb6aaa0,0xb137ac7d,0xb418b20a,0xb580b412,0xb62fb527,0xb81ab6e1,0xb814b730,0xb94eb8b9,
0x36f837fd,0x388b3928,0x34d435ea,0x366337c6,0x312b336e,0x32e734f1,0x249d2dc3,0x262f2fb6,0xb007aaeb,0xb163aca2,0xb446b24e,0xb5acb434,0xb672b55f,0xb838b717,0xb83eb77c,0xb972b8db,
0x38ab394b,0x399b3a45,0x36943800,0x380838db,0x331e3518,0x346a3649,0x26612ff5,0x27f330f3,0xb18eacc8,0xb2e7adf5,0xb5d8b455,0xb730b55d,0xb857b74c,0xb93eb874,0xb996b8fd,0xba91b9f3,
0x38cb396d,0x39b73a61,0x36c5381c,0x381f38f5,0x3356353f,0x3485366f,0x2694301a,0x28133112,0xb1b9acee,0xb312ae1a,0xb604b476,0xb75ab57d,0xb875b781,0xb959b88c,0xb9b8b91e,0xbaadba0f,
0x38ea398e,0x39d23a7c,0x36f53838,0x3836390f,0x338d3565,0x34a03694,0x26c63039,0x282c3131,0xb1e5ad13,0xb33dae40,0xb62fb497,0xb784b59d,0xb893b7b6,0xb974b8a5,0xb9dab93e,0xbac7ba2b,
0x390939ae,0x39ed3a97,0x37253854,0x384c3928,0x33c3358c,0x34bc36b9,0x26f83058,0x28453150,0xb210ad39,0xb368ae65,0xb65bb4b9,0xb7adb5be,0xb8b0b7ea,0xb98eb8bd,0xb9fbb95e,0xbae0ba45,
0x392739ce,0x3a073ab0,0x37553870,0x38633941,0x33fa35b2,0x34d736de,0x272a3077,0x285e316f,0xb23bad5e,0xb393ae8b,0xb686b4da,0xb7d7b5de,0xb8cdb80f,0xb9a8b8d5,0xba1bb97d,0xbaf9ba5f,
0x394539ed,0x3a213ac9,0x3784388b,0x3879395a,0x341835d8,0x34f13703,0x275d3096,0x2877318e,0xb266ad84,0xb3bdaeb0,0xb6b1b4fa,0xb800b5fe,0xb8eab828,0xb9c1b8ed,0xba3ab99b,0xbb10ba79,
0x39623a0b,0x3a3a3ae0,0x37b338a6,0x388f3972,0x343435fe,0x350c3728,0x278f30b5,0x289031ad,0xb291adaa,0xb3e8aed6,0xb6dcb51b,0xb814b61e,0xb906b842,0xb9dab904,0xba58b9b9,0xbb26ba91,
0x397f3a29,0x3a523af7,0x37e238c1,0x38a5398a,0x344f3624,0x3527374c,0x27c130d4,0x28aa31cc,0xb2bcadcf,0xb409aefb,0xb706b53c,0xb828b63e,0xb922b85b,0xb9f2b91b,0xba75b9d7,0xbb3cbaa9,
0x3a6a3b0d,0x3b113b9c,0x38bb39a2,0x39603a51,0x35423770,0x36153846,0x28c331eb,0x298c32e1,0xb41faf21,0xb4c8b026,0xb83cb65e,0xb8d7b757,0xba0ab932,0xbab8b9de,0xbb50bac0,0xbbcbbb5e,
0x3a813b22,0x3b243ba9,0x38d039b9,0x39743a65,0x355d3795,0x362f3857,0x28dc320a,0x29a53300,0xb434af46,0xb4ddb039,0xb850b67d,0xb8eab776,0xba22b949,0xbacbb9f2,0xbb63bad7,0xbbd6bb6e,
0x3a973b36,0x3b353bb6,0x38e539d0,0x39873a79,0x357737b8,0x36493868,0x28f53229,0x29be331e,0xb449af6c,0xb4f1b04b,0xb864b69d,0xb8fdb795,0xba39b95f,0xbadeba06,0xbb75baec,0xbbdfbb7d,
0x3aad3b4a,0x3b463bc2,0x38fa39e7,0x399a3a8c,0x359237dc,0x36633879,0x290e3247,0x29d7333d,0xb45eaf91,0xb506b05e,0xb878b6bc,0xb90fb7b3,0xba4fb975,0xbaf0ba19,0xbb86bb01,0xbbe7bb8c,
0x3ac33b5c,0x3b563bcc,0x390f39fd,0x39ad3a9f,0x35ac3800,0x367d388a,0x29273266,0x29f0335c,0xb473afb6,0xb51bb071,0xb88bb6dc,0xb921b7d1,0xba65b98a,0xbb02ba2d,0xbb96bb15,0xbbeebb99,
0x3ad73b6d,0x3b653bd6,0x39243a12,0x39c03ab1,0x35c73811,0x3697389b,0x29403285,0x2a09337a,0xb488afdc,0xb530b083,0xb89eb6fb,0xb933b7ef,0xba7ab9a0,0xbb13ba3f,0xbba5bb28,0xbbf4bba6,
0x3aeb3b7e,0x3b743bdf,0x39383a28,0x39d23ac3,0x35e13823,0x36b138ab,0x295932a4,0x2a223399,0xb49db001,0xb545b096,0xb8b2b71a,0xb945b807,0xba8fb9b5,0xbb24ba52,0xbbb3bb3b,0xbbf9bbb2,
0x3aff3b8d,0x3b823be6,0x394c3a3c,0x39e43ad4,0x35fb3834,0x36ca38bc,0x297232c2,0x2a3b33b7,0xb4b3b013,0xb55ab0a9,0xb8c5b739,0xb957b815,0xbaa4b9ca,0xbb34ba64,0xbbc0bb4d,0xbbfcbbbd,
0x39b839ba,0x3a973ab5,0x39b339b5,0x3a583a78,0x39af39b1,0x3a153a37,0x39aa39ad,0x39cd39f2,0x39a639a8,0x398239a8,0x39a139a4,0x3933395b,0x399d399f,0x38e03909,0x3999399b,0x388938b5,
0xb979b972,0xb865b832,0xb986b980,0xb8c7b896,0xb994b98d,0xb924b8f6,0xb9a1b99b,0xb97db951,0xb9afb9a8,0xb9d2b9a8,0xb9bcb9b5,0xba21b9fa,0xb9c9b9c3,0xba6bba47,0xb9d6b9d0,0xbab0ba8e,
0xb9f4b9fe,0xbac7bae9,0xb9dfb9e9,0xba7ebaa3,0xb9c9b9d4,0xba2dba56,0xb9b3b9be,0xb9d6ba02,0xb99db9a8,0xb979b9a8,0xb986b992,0xb916b948,0xb970b97b,0xb8adb8e2,0xb958b964,0xb840b877,
0x39373927,0x381a37b7,0x39583948,0x38943858,0x39793969,0x390738ce,0x39993989,0x3974393e,0x39b839a8,0x39da39a8,0x39d639c7,0x3a393a0b,0x39f439e5,0x3a903a65,0x3a113a02,0x3ade3ab8,
0x3a2d3a3f,0x3af43b1a,0x3a093a1b,0x3aa23acc,0x39e339f6,0x3a453a74,0x39bc39d0,0x39df3a13,0x399439a8,0x397039a8,0x396b3980,0x38f83935,0x39413956,0x387a38ba,0x3916392b,0x37e83838,
0xb8f3b8d8,0xb79bb705,0xb929b90e,0xb85fb817,0xb95db943,0xb8eab8a6,0xb990b976,0xb96bb92b,0xb9c0b9a8,0xb9e3b9a8,0xb9f0b9d8,0xba50ba1b,0xba1dba07,0xbab3ba83,0xba49ba33,0xbb0abae0,
0xba64ba7c,0xbb1ebb46,0xba31ba4b,0xbac4baf3,0xb9fcba17,0xba5cba92,0xb9c5b9e1,0xb9e7ba23,0xb98bb9a8,0xb966b9a8,0xb94fb96d,0xb8dbb922,0xb911b930,0xb845b891,0xb8d1b8f1,0xb74eb7ee,
0x38ad3887,0x36ff364e,0x38f838d3,0x382a37ac,0x3941391d,0x38cc387c,0x39863964,0x39623918,0x39c939a8,0x39eb39a8,0x3a0939e9,0x3a673a2b,0x3a453a27,0x3ad53aa0,0x3a7e3a62,0x3b323b05,
0x3b453b6e,0x3bbc3bdd,0x3ae53b17,0x3b573b8f,0x3a733aae,0x3ac73b14,0x39f03a33,0x3a113a71,0x395d39a8,0x393739a8,0x38bc390e,0x384038bf,0x380f3867,0x365f3775,0x36af376a,0x341a3540,
0xb65fb593,0xb389b115,0xb7e8b726,0xb625b4f9,0xb8adb852,0xb830b748,0xb958b905,0xb933b8b5,0xb9f4b9a8,0xba15b9a8,0xba7eba3b,0xbad1ba78,0xbaf4babc,0xbb63bb20,0xbb57bb28,0xbbc6bb9b,
0xbb68bb91,0xbbd0bbed,0xbb04bb39,0xbb6fbba6,0xba89bac9,0xbadbbb2b,0xb9f8ba43,0xba19ba7f,0xb954b9a8,0xb92eb9a8,0xb89eb8fb,0xb820b8ab,0xb7b2b83d,0xb5ebb71b,0xb60eb6e3,0xb2deb4b1,
0x35bc34d5,0x32322f0e,0x377a369e,0x35b13469,0x388e3828,0x380f36ee,0x394f38f1,0x392938a0,0x39fc39a8,0x3a1d39a8,0x3a933a4b,0x3ae53a87,0x3b133ad6,0x3b7a3b36,0x3b783b49,0x3bd93bb1,
0x3b873baf,0x3be13bf8,0x3b213b58,0x3b853bbb,0x3a9e3ae3,0x3aee3b41,0x3a003a52,0x3a213a8e,0x394a39a8,0x392439a8,0x387f38e7,0x37fe3896,0x37423812,0x357636c1,0x356a3659,0x31853420,
0xb517b414,0xb0d7abd9,0xb70ab614,0xb53ab3ae,0xb86fb7f9,0xb7ddb693,0xb946b8dd,0xb91fb88c,0xba04b9a8,0xba25b9a8,0xbaa9ba5a,0xbaf7ba95,0xbb2fbaf0,0xbb90bb4b,0xbb96bb67,0xbbe8bbc4,
0xbba3bbc9,0xbbefbbff,0xbb3dbb74,0xbb9abbcd,0xbab3bafc,0xbb01bb55,0xba09ba62,0xba29ba9c,0xb941b9a8,0xb91bb9a8,0xb85fb8d3,0xb7bdb881,0xb6d2b7cd,0xb4ffb665,0xb4c3b5ce,0xb029b31b,
0x346f32a1,0x2ef52248,0x36993587,0x34c33288,0x385037a1,0x379b3637,0x393c38c9,0x39163877,0x3a0d39a8,0x3a2d39a8,0x3abd3a69,0x3b0a3aa3,0x3b4a3b08,0x3ba33b5f,0x3bb03b82,0x3bf43bd5,
0x3bf83c00,0x3bf93bd4,0x3bac3bdc,0x3be43bfe,0x3b133b69,0x3b543bab,0x3a313aaa,0x3a503ae0,0x391139a8,0x38ea39a8,0x377a386d,0x366b3817,0x34873608,0x313b348d,0x2d9731f4,0xad65291b,
0xac3828b6,0x2ec33365,0xb44bb160,0xb0bea57f,0xb759b5da,0xb648b45d,0xb90cb862,0xb8e5b80d,0xba35b9a8,0xba54b9a8,0xbb1bbab1,0xbb5cbae6,0xbbb5bb72,0xbbe9bbb2,0xbbfcbbe3,0xbbf5bc00,
0xbbfebbfc,0xbbefbbbc,0xbbbdbbe9,0xbbeebc00,0xbb24bb7b,0xbb63bbb9,0xba39bab8,0xba58baed,0xb907b9a8,0xb8e0b9a8,0xb737b858,0xb625b802,0xb40eb5ab,0xb042b42c,0xa9b1b0cb,0x30109a48,
0x25e4ad7e,0xb0beb475,0x33a23036,0x2f8ba3db,0x3715357c,0x360233f7,0x3902384d,0x38db37ee,0x3a3d39a8,0x3a5c39a8,0x3b2c3abf,0x3b6a3af3,0x3bc53b84,0x3bf23bc0,0x3bff3bee,0x3be93c00,
0x3c003bf4,0x3be23ba0,0x3bcc3bf3,0x3bf53bff,0x3b353b8c,0x3b713bc6,0x3a413ac6,0x3a603af9,0x38fd39a8,0x38d639a8,0x36f43842,0x35df37d8,0x3328354c,0x2e913396,0x16482f40,0xb16ca852,
0x251b304e,0x32193534,0xb2adae14,0xad972aac,0xb6d2b51d,0xb5bcb334,0xb8f8b838,0xb8d1b7c2,0xba45b9a8,0xba64b9a8,0xbb3dbacc,0xbb78baff,0xbbd3bb95,0xbbf8bbcb,0xbc00bbf7,0xbbdabbfd,
0xbbfebbe6,0xbbd2bb80,0xbbd9bbfa,0xbbfbbbfb,0xbb45bb9d,0xbb7fbbd1,0xba49bad3,0xba67bb05,0xb8f3b9a8,0xb8ccb9a8,0xb6afb82d,0xb599b7ac,0xb232b4ed,0xac9cb2d2,0x294dace7,0x32c62c83,
0xac06b1db,0xb371b5f1,0x31b62b75,0x2b43adb0,0x368d34bd,0x3576326f,0x38ee3822,0x38c73796,0x3a4d39a8,0x3a6b39a8,0x3b4c3ad9,0x3b853b0b,0x3bdf3ba4,0x3bfd3bd6,0x3bfc3bfd,0x3bc83bf8,
0x3bbd3b5a,0x3b473a99,0x3bfe3bf4,0x3bf93bbe,0x3b8b3bdb,0x3bb83bf7,0x3a6f3b11,0x3a8c3b3e,0x38c139a8,0x389939a8,0x35523780,0x343236cc,0x294d320d,0xad332de2,0xb40eaedc,0xb6a4b408,
0x346336aa,0x36f438b0,0xa6ad3004,0x2e2d3451,0xb52fb1aa,0xb40ead1a,0xb8bcb76a,0xb894b6b5,0xba73b9a8,0xba90b9a8,0xbb92bb17,0xbbbdbb43,0xbbffbbe0,0xbbf6bbf9,0xbbb2bbf0,0xbb35bbb4,
0xbba5bb30,0xbb21ba5e,0xbc00bbeb,0xbbf3bbaa,0xbb98bbe4,0xbbc2bbfb,0xba76bb1d,0xba93bb49,0xb8b7b9a8,0xb88eb9a8,0xb50bb753,0xb3d3b69e,0xa17fb147,0x2f27ac51,0x34b73099,0x37423499,
0xb50bb75e,0xb790b900,0x9cb6b12e,0xb010b4e1,0x34e730e4,0x33892b11,0x38b2373d,0x38893687,0x3a7a39a8,0x3a9739a8,0x3b9e3b22,0x3bc63b4e,0x3c003be8,0x3bef3bfd,0x3b983be5,0x3b0d3b9e,
0x3b893b02,0x3af73a1f,0x3c003bdf,0x3beb3b93,0x3ba33bec,0x3bcb3bfe,0x3a7e3b28,0x3a9b3b53,0x38ad39a8,0x388439a8,0x34c33726,0x33403670,0xa51b3080,0xb08d297f,0xb55eb1c3,0xb7ddb529,
0x35b13807,0x3815394d,0x28843257,0x31093570,0xb49fb01d,0xb2f7a7da,0xb8a8b710,0xb87fb659,0xba81b9a8,0xba9eb9a8,0xbba9bb2e,0xbbcfbb58,0xbbffbbef,0xbbe6bbff,0xbb7abbd7,0xbae1bb86,
0xbb6abad0,0xbacbb9dc,0xbbfdbbd0,0xbbe1bb79,0xbbaebbf2,0xbbd3bc00,0xba85bb33,0xbaa2bb5d,0xb8a3b9a8,0xb87ab9a8,0xb47bb6f9,0xb2adb642,0x2a7aaf72,0x3185a4b6,0x360232ea,0x383a35b6,
0xb654b85d,0xb85fb996,0xac38b37d,0xb201b5fd,0x34572eaa,0x32631e48,0x389e36e3,0x3874362b,0x3a8939a8,0x3aa539a8,0x3bb33b39,0x3bd73b62,0x3bfc3bf5,0x3bdc3c00,0x3b593bc7,0x3ab33b6b,
0x39b739b9,0x3a883aa6,0x39b239b4,0x3a483a68,0x39ae39b0,0x3a033a26,0x39a939ab,0x39bb39e0,0x39a539a7,0x396e3995,0x39a039a3,0x391e3947,0x399c399e,0x38ca38f5,0x3997399a,0x3873389f,
0xb97cb975,0xb87eb84c,0xb98ab983,0xb8deb8ae,0xb997b991,0xb93bb90d,0xb9a5b99e,0xb993b967,0xb9b2b9ab,0xb9e6b9bd,0xb9bfb9b9,0xba34ba0e,0xb9ccb9c6,0xba7dba59,0xb9d9b9d3,0xbac0ba9f,
0xb9efb9f9,0xbab6bad9,0xb9d9b9e4,0xba6aba91,0xb9c4b9cf,0xba18ba42,0xb9aeb9b9,0xb9bfb9ec,0xb997b9a3,0xb961b991,0xb981b98c,0xb8fcb92f,0xb96ab975,0xb892b8c8,0xb953b95e,0xb824b85c,
0x3940392f,0x383937f6,0x39613950,0x38b13876,0x39813971,0x392338eb,0x39a03991,0x398e395a,0x39bf39b0,0x39f339c1,0x39de39cf,0x3a4f3a22,0x39fb39ec,0x3aa43a7b,0x3a183a0a,0x3af03acb,
0x3a243a36,0x3ae13b07,0x39ff3a12,0x3a8b3ab7,0x39d939ec,0x3a2c3a5d,0x39b239c6,0x39c439f9,0x398a399e,0x3953398c,0x39613975,0x38d93917,0x3936394b,0x3859389a,0x390b3921,0x37a43816,
0xb901b8e6,0xb7e6b750,0xb936b91c,0xb883b83c,0xb96ab950,0xb90bb8c8,0xb99cb983,0xb98ab94b,0xb9ccb9b4,0xb9ffb9c6,0xb9fbb9e4,0xba6aba36,0xba28ba12,0xbacaba9b,0xba53ba3e,0xbb1dbaf5,
0xba57ba70,0xbb09bb33,0xba24ba3e,0xbaabbadc,0xb9efba0a,0xba40ba77,0xb9b7b9d3,0xb9c8ba05,0xb97cb99a,0xb944b988,0xb940b95e,0xb8b6b8fe,0xb901b921,0xb81eb86b,0xb8c0b8e1,0xb6fcb79e,
0x38c0389a,0x375636a7,0x390b38e6,0x38543800,0x3953392f,0x38f238a4,0x39973975,0x3985393d,0x39d939b9,0x3a0c39ca,0x3a1839f9,0x3a843a4a,0x3a533a36,0x3aed3abb,0x3a8b3a70,0x3b473b1c,
0x3b2e3b5a,0x3ba63bce,0x3aca3afe,0x3b373b74,0x3a533a91,0x3a9d3aef,0x39cc3a12,0x39de3a42,0x39363983,0x38fc3971,0x389238e6,0x37fb3880,0x37c5383c,0x35d136eb,0x3651370d,0x330934ae,
0xb6c3b5fa,0xb460b251,0xb824b788,0xb6b8b590,0xb8d9b880,0xb873b7d5,0xb981b92f,0xb96eb8f5,0xba18b9cf,0xba48b9e0,0xba9dba5d,0xbafabaa6,0xbb0fbad9,0xbb80bb43,0xbb6cbb40,0xbbd8bbb2,
0xbb51bb7d,0xbbbdbbe0,0xbae7bb1f,0xbb4ebb8c,0xba66baa9,0xbaafbb04,0xb9d1ba1e,0xb9e2ba4e,0xb928b97e,0xb8edb96c,0xb86eb8cd,0xb7afb866,0xb74bb80b,0xb54fb684,0xb5a2b679,0xb197b411,
0x362e3549,0x338330de,0x37e6370d,0x3651350e,0x38c0385c,0x38593788,0x397c3921,0x396a38e6,0x3a2439d3,0x3a5339e4,0x3ab63a70,0x3b0f3ab7,0x3b2e3af5,0x3b973b5a,0x3b8d3b61,0x3be83bc7,
0x3b703b9c,0x3bd03bef,0x3b033b3d,0x3b653ba2,0x3a793ac1,0x3ac03b19,0x39d53a2a,0x39e63a59,0x3919397a,0x38de3967,0x384938b4,0x3761384c,0x36cf37b4,0x34cc361d,0x34f035e2,0x302332e4,
0xb596b496,0xb244aecf,0xb783b690,0xb5e8b48a,0xb8a7b836,0xb83eb73a,0xb978b912,0xb965b8d7,0xba30b9d7,0xba5fb9e8,0xbacdba82,0xbb23bac8,0xbb4cbb10,0xbbacbb6f,0xbbaabb7f,0xbbf4bbd8,
0xbb8dbbb7,0xbbe0bbf9,0xbb1dbb5a,0xbb7abbb5,0xba8bbad9,0xbad0bb2d,0xb9d9ba36,0xb9eaba65,0xb90bb975,0xb8cfb963,0xb824b89a,0xb713b831,0xb651b750,0xb447b5b3,0xb43bb549,0xad58b1a4,
0x34fc33c0,0x31032bc0,0x371e3611,0x357e3405,0x388d3811,0x382436eb,0x39733903,0x396138c8,0x3a3c39db,0x3a6a39ec,0x3ae43a94,0x3b373ad9,0x3b673b2a,0x3bbe3b83,0x3bc33b9a,0x3bfc3be7,
0x3bed3bff,0x3bff3bea,0x3b8d3bc7,0x3bcc3bf5,0x3ae13b40,0x3b1d3b83,0x39ef3a70,0x39ff3a9b,0x38c0395e,0x3883394b,0x36c33816,0x357e3750,0x33833549,0x2e84332e,0x28cf3061,0xb0aca5b2,
0xaf7ea376,0x29663166,0xb514b2fd,0xb2bfad71,0xb809b69b,0xb734b555,0xb95cb8b9,0xb949b87b,0xba75b9f1,0xbaa1ba01,0xbb49bae9,0xbb8bbb25,0xbbcfbb96,0xbbf9bbd2,0xbc00bbf2,0xbbe3bbfe,
0xbbf6bc00,0xbbfcbbda,0xbb9fbbd6,0xbbd8bbfb,0xbaf0bb52,0xbb2cbb92,0xb9f3ba7b,0xba03baa6,0xb8b1b95a,0xb873b947,0xb673b7f6,0xb52cb718,0xb276b4de,0xac5eb251,0x2052ae39,0x321f2bf2,
0x2cf4a806,0xad3fb2d8,0x34a831ee,0x31e22a93,0x37db364b,0x36fc3502,0x395738a9,0x3944386b,0x3a8039f5,0x3aab3a05,0x3b5b3af8,0x3b993b33,0x3bdd3ba7,0x3bfd3bdd,0x3bff3bfa,0x3bd13bf9,
0x3bfd3bfd,0x3bf53bc6,0x3baf3be3,0x3be23bff,0x3b003b64,0x3b393ba0,0x39f73a86,0x3a083ab0,0x38a23955,0x38633942,0x362237bf,0x34d836e0,0x31663472,0x286b3172,0xaaf82b5c,0xb390ae84,
0xa8cf2cf4,0x2fc93423,0xb43bb0de,0xb103a484,0xb7a4b5fa,0xb6c3b4ae,0xb953b89a,0xb940b85c,0xba8bb9f9,0xbab6ba0a,0xbb6cbb07,0xbba6bb40,0xbbe8bbb7,0xbc00bbe7,0xbbfabbff,0xbbbabbf1,
0xbc00bbf6,0xbbebbbae,0xbbbebbed,0xbbebbc00,0xbb0fbb74,0xbb47bbad,0xb9fbba91,0xba0cbabb,0xb892b950,0xb854b93d,0xb5d1b788,0xb484b6a7,0xb055b405,0x9248b093,0x2e6ba484,0x347e3086,
0x98b6afe2,0xb128b4d8,0x339c2f97,0x3023a420,0x376c35a8,0x368a345a,0x394e388b,0x393b384c,0x3a9639fd,0x3ac03a0e,0x3b7c3b16,0x3bb33b4d,0x3bf23bc5,0x3c003bef,0x3bf03c00,0x3ba03be5,
0x3bde3b91,0x3b8a3af7,0x3bf23bff,0x3c003be3,0x3b533bb9,0x3b823bdf,0x3a103ac5,0x3a203aec,0x38443939,0x38033925,0x342f366d,0x31b03584,0xa8392f65,0xb15a1d7f,0xb531b1c9,0xb7e0b55b,
0x3269358a,0x35a83819,0xae842a61,0x205231e2,0xb651b405,0xb567b15a,0xb936b83c,0xb923b7f6,0xbacaba12,0xbaf0ba22,0xbbbebb5a,0xbbe3bb88,0xbbfdbbf5,0xbbddbc00,0xbb81bbd6,0xbadfbb7c,
0xbbcebb70,0xbb6dbac6,0xbbf8bbfb,0xbbffbbd6,0xbb60bbc4,0xbb8dbbe7,0xba14bacf,0xba24baf5,0xb834b934,0xb7e6b921,0xb3b4b634,0xb103b549,0x2c44ada3,0x326925b2,0x35e23309,0x384135f4,
0xb3a8b63a,0xb63fb869,0x2cc2ad58,0xa89db2f0,0x3617335f,0x352c30ac,0x3931382c,0x391e37d5,0x3ad43a16,0x3afa3a26,0x3bc93b66,0x3bea3b92,0x3bf93bfa,0x3bcf3bff,0x3b5f3bc5,0x3aad3b5d,
0x3bba3b4c,0x3b4d3a93,0x3bfc3bf6,0x3bfd3bc7,0x3b6c3bce,0x3b973bed,0x3a183ad9,0x3a283afe,0x3824392f,0x37c5391c,0x330935fa,0x3055350e,0xae6b2bc0,0xb377aa61,0xb690b423,0xb890b68a,
0x347236e5,0x36d438b6,0xa9fd2f7e,0x2c1233fd,0xb5dcb2b3,0xb4f0affb,0xb92db81c,0xb919b7b4,0xbaddba1a,0xbb03ba2a,0xbbd3bb72,0xbbf0bb9c,0xbbf2bbfe,0xbbbfbbfc,0xbb38bbaf,0xba77bb3c,
0xbba4bb23,0xbb2aba5b,0xbbffbbee,0xbbfabbb6,0xbb77bbd7,0xbba1bbf3,0xba1cbae2,0xba2cbb07,0xb813b92a,0xb7a4b917,0xb25db5bf,0xaf4cb4d2,0x3048a839,0x34412cf4,0x373a34c0,0x38dc371e,
0xb50eb78e,0xb767b901,0x24e9b0d1,0xadd5b484,0x35a23207,0x34b42e9d,0x3928380b,0x39143793,0x3ae73a1e,0x3b0c3a2e,0x3bdb3b7d,0x3bf53ba6,0x3be93c00,0x3bad3bf7,0x3b0d3b97,0x3a3e3b18,
0xb999b996,0xb889b85d,0xb99db99b,0xb8e0b8b5,0xb9a1b99f,0xb933b909,0xb9a6b9a4,0xb982b95b,0xb9aab9a8,0xb9cdb9a8,0xb9afb9ad,0xba15b9f2,0xb9b3b9b1,0xba58ba37,0xb9b8b9b5,0xba97ba78,
0xb9d6b9dc,0xbab0bad0,0xb9c9b9d0,0xba6bba8e,0xb9bcb9c3,0xba21ba47,0xb9afb9b5,0xb9d2b9fa,0xb9a1b9a8,0xb97db9a8,0xb994b99b,0xb924b951,0xb986b98d,0xb8c7b8f6,0xb979b980,0xb865b896,
0x3958394d,0x38403807,0x39703964,0x38ad3877,0x3986397b,0x391638e2,0x399d3992,0x39793948,0x39b339a8,0x39d639a8,0x39c939be,0x3a2d3a02,0x39df39d4,0x3a7e3a56,0x39f439e9,0x3ac73aa3,
0x3a113a1f,0x3ade3b02,0x39f43a02,0x3a903ab8,0x39d639e5,0x3a393a65,0x39b839c7,0x39da3a0b,0x399939a8,0x397439a8,0x39793989,0x3907393e,0x39583969,0x389438ce,0x39373948,0x381a3858,
0xb916b900,0xb7e8b75e,0xb941b92b,0xb87ab838,0xb96bb956,0xb8f8b8ba,0xb994b980,0xb970b935,0xb9bcb9a8,0xb9dfb9a8,0xb9e3b9d0,0xba45ba13,0xba09b9f6,0xbaa2ba74,0xba2dba1b,0xbaf4bacc,
0xba49ba5e,0xbb0abb30,0xba1dba33,0xbab3bae0,0xb9f0ba07,0xba50ba83,0xb9c0b9d8,0xb9e3ba1b,0xb990b9a8,0xb96bb9a8,0xb95db976,0xb8eab92b,0xb929b943,0xb85fb8a6,0xb8f3b90e,0xb79bb817,
0x38d138b0,0x374e36aa,0x391138f1,0x384537ee,0x394f3930,0x38db3891,0x398b396d,0x39663922,0x39c539a8,0x39e739a8,0x39fc39e1,0x3a5c3a23,0x3a313a17,0x3ac43a92,0x3a643a4b,0x3b1e3af3,
0x3a7e3a99,0x3b323b5a,0x3a453a62,0x3ad53b05,0x3a093a27,0x3a673aa0,0x39c939e9,0x39eb3a2b,0x398639a8,0x396239a8,0x39413964,0x38cc3918,0x38f8391d,0x382a387c,0x38ad38d3,0x36ff37ac,
0xb6afb5f1,0xb41ab1db,0xb80fb76a,0xb65fb540,0xb8bcb867,0xb840b775,0xb95db90e,0xb937b8bf,0xb9f0b9a8,0xba11b9a8,0xba73ba33,0xbac7ba71,0xbae5baae,0xbb57bb14,0xbb45bb17,0xbbbcbb8f,
0xbb57bb80,0xbbc6bbe6,0xbaf4bb28,0xbb63bb9b,0xba7ebabc,0xbad1bb20,0xb9f4ba3b,0xba15ba78,0xb958b9a8,0xb933b9a8,0xb8adb905,0xb830b8b5,0xb7e8b852,0xb625b748,0xb65fb726,0xb389b4f9,
0x360e3534,0x32de304e,0x37b236e3,0x35eb34b1,0x389e383d,0x3820371b,0x395438fb,0x392e38ab,0x39f839a8,0x3a1939a8,0x3a893a43,0x3adb3a7f,0x3b043ac9,0x3b6f3b2b,0x3b683b39,0x3bd03ba6,
0x3b783ba0,0x3bd93bf4,0x3b133b49,0x3b7a3bb1,0x3a933ad6,0x3ae53b36,0x39fc3a4b,0x3a1d3a87,0x394f39a8,0x392939a8,0x388e38f1,0x380f38a0,0x377a3828,0x35b136ee,0x35bc369e,0x32323469,
0xb56ab475,0xb185ad7e,0xb742b659,0xb576b420,0xb87fb812,0xb7feb6c1,0xb94ab8e7,0xb924b896,0xba00b9a8,0xba21b9a8,0xba9eba52,0xbaeeba8e,0xbb21bae3,0xbb85bb41,0xbb87bb58,0xbbe1bbbb,
0xbb96bbbc,0xbbe8bbfc,0xbb2fbb67,0xbb90bbc4,0xbaa9baf0,0xbaf7bb4b,0xba04ba5a,0xba25ba95,0xb946b9a8,0xb91fb9a8,0xb86fb8dd,0xb7ddb88c,0xb70ab7f9,0xb53ab693,0xb517b614,0xb0d7b3ae,
0x34c33365,0x302928b6,0x36d235ce,0x34ff331b,0x385f37cd,0x37bd3665,0x394138d3,0x391b3881,0x3a0939a8,0x3a2939a8,0x3ab33a62,0x3b013a9c,0x3b3d3afc,0x3b9a3b55,0x3ba33b74,0x3bef3bcd,
0x3bb03bd4,0x3bf43c00,0x3b4a3b82,0x3ba33bd5,0x3abd3b08,0x3b0a3b5f,0x3a0d3a69,0x3a2d3aa3,0x393c39a8,0x391639a8,0x385038c9,0x379b3877,0x369937a1,0x34c33637,0x346f3587,0x2ef53288,
0xad972248,0x2d6532a1,0xb487b1f4,0xb13ba91b,0xb77ab608,0xb66bb48d,0xb911b86d,0xb8eab817,0xba31b9a8,0xba50b9a8,0xbb13baaa,0xbb54bae0,0xbbacbb69,0xbbe4bbab,0xbbf8bbdc,0xbbf9bbfe,
0xbbfcbbff,0xbbf5bbc9,0xbbb5bbe3,0xbbe9bc00,0xbb1bbb72,0xbb5cbbb2,0xba35bab1,0xba54bae6,0xb90cb9a8,0xb8e5b9a8,0xb759b862,0xb648b80d,0xb44bb5da,0xb0beb45d,0xac38b160,0x2ec3a57f,
0x29b1abd9,0xb010b414,0x340e30cb,0x30421a48,0x373735ab,0x3625342c,0x39073858,0x38e03802,0x3a3939a8,0x3a5839a8,0x3b243ab8,0x3b633aed,0x3bbd3b7b,0x3bee3bb9,0x3bfe3be9,0x3bef3c00,
0x3bff3bf8,0x3be93baf,0x3bc53bee,0x3bf23c00,0x3b2c3b84,0x3b6a3bc0,0x3a3d3abf,0x3a5c3af3,0x390239a8,0x38db39a8,0x3715384d,0x360237ee,0x33a2357c,0x2f8b33f7,0x25e43036,0xb0bea3db,
0x96482f0e,0x316c34d5,0xb328af40,0xae912852,0xb6f4b54c,0xb5dfb396,0xb8fdb842,0xb8d6b7d8,0xba41b9a8,0xba60b9a8,0xbb35bac6,0xbb71baf9,0xbbccbb8c,0xbbf5bbc6,0xbc00bbf3,0xbbe2bbff,
0xbc00bbed,0xbbdabb91,0xbbd3bbf7,0xbbf8bbfd,0xbb3dbb95,0xbb78bbcb,0xba45bacc,0xba64baff,0xb8f8b9a8,0xb8d1b9a8,0xb6d2b838,0xb5bcb7c2,0xb2adb51d,0xad97b334,0x251bae14,0x32192aac,
0xa94db115,0xb2c6b593,0x32322ce7,0x2c9cac83,0x36af34ed,0x359932d2,0x38f3382d,0x38cc37ac,0x3a4939a8,0x3a6739a8,0x3b453ad3,0x3b7f3b05,0x3bd93b9d,0x3bfb3bd1,0x3bfe3bfa,0x3bd23bfb,
0x3bfc3bdd,0x3bc83b6e,0x3bdf3bfd,0x3bfd3bf8,0x3b4c3ba4,0x3b853bd6,0x3a4d3ad9,0x3a6b3b0b,0x38ee39a8,0x38c739a8,0x368d3822,0x35763796,0x31b634bd,0x2b43326f,0xac062b75,0xb371adb0,
0x340e364e,0x36a43887,0xa94d2edc,0x2d333408,0xb552b20d,0xb432ade2,0xb8c1b780,0xb899b6cc,0xba6fb9a8,0xba8cb9a8,0xbb8bbb11,0xbbb8bb3e,0xbbfebbdb,0xbbf9bbf7,0xbbbdbbf4,0xbb47bbbe,
0xbbb2bb46,0xbb35ba7c,0xbbffbbf0,0xbbf6bbb4,0xbb92bbe0,0xbbbdbbf9,0xba73bb17,0xba90bb43,0xb8bcb9a8,0xb894b9a8,0xb52fb76a,0xb40eb6b5,0xa6adb1aa,0x2e2dad1a,0x34633004,0x36f43451,
0xb4b7b705,0xb742b8d8,0x217fb099,0xaf27b499,0x350b3147,0x33d32c51,0x38b73753,0x388e369e,0x3a7639a8,0x3a9339a8,0x3b983b1d,0x3bc23b49,0x3c003be4,0x3bf33bfb,0x3ba53beb,0x3b213baa,
0x3b983b1a,0x3b0d3a3f,0x3c003be5,0x3bef3b9e,0x3b9e3be8,0x3bc63bfd,0x3a7a3b22,0x3a973b4e,0x38b239a8,0x388939a8,0x34e7373d,0x33893687,0x9cb630e4,0xb0102b11,0xb50bb12e,0xb790b4e1,
0x355e37b7,0x37dd3927,0x251b31c3,0x308d3529,0xb4c3b080,0xb340a97f,0xb8adb726,0xb884b670,0xba7eb9a8,0xba9bb9a8,0xbba3bb28,0xbbcbbb53,0xbc00bbec,0xbbebbbfe,0xbb89bbdf,0xbaf7bb93,
0xbb7abae9,0xbae1b9fe,0xbbffbbd7,0xbbe6bb86,0xbba9bbef,0xbbcfbbff,0xba81bb2e,0xba9ebb58,0xb8a8b9a8,0xb87fb9a8,0xb49fb710,0xb2f7b659,0x2884b01d,0x3109a7da,0x35b13257,0x38153570,
0xb602b832,0xb83ab972,0xaa7ab2ea,0xb185b5b6,0x347b2f72,0x32ad24b6,0x38a336f9,0x387a3642,0x3a8539a8,0x3aa239a8,0x3bae3b33,0x3bd33b5d,0x3bfd3bf2,0x3be13c00,0x3b6a3bd0,0x3acb3b79,
0x3b593ab5,0x3ab339ba,0x3bfc3bc7,0x3bdc3b6b,0x3bb33bf5,0x3bd73c00,0x3a893b39,0x3aa53b62,0x389e39a8,0x387439a8,0x345736e3,0x3263362b,0xac382eaa,0xb2011e48,0xb654b37d,0xb85fb5fd,
0xb99ab997,0xb89fb873,0xb99eb99c,0xb8f5b8ca,0xb9a3b9a0,0xb947b91e,0xb9a7b9a5,0xb995b96e,0xb9abb9a9,0xb9e0b9bb,0xb9b0b9ae,0xba26ba03,0xb9b4b9b2,0xba68ba48,0xb9b9b9b7,0xbaa6ba88,
0xb9d3b9d9,0xba9fbac0,0xb9c6b9cc,0xba59ba7d,0xb9b9b9bf,0xba0eba34,0xb9abb9b2,0xb9bdb9e6,0xb99eb9a5,0xb967b993,0xb991b997,0xb90db93b,0xb983b98a,0xb8aeb8de,0xb975b97c,0xb84cb87e,
0x395e3953,0x385c3824,0x3975396a,0x38c83892,0x398c3981,0x392f38fc,0x39a33997,0x39913961,0x39b939ae,0x39ec39bf,0x39cf39c4,0x3a423a18,0x39e439d9,0x3a913a6a,0x39f939ef,0x3ad93ab6,
0x3a0a3a18,0x3acb3af0,0x39ec39fb,0x3a7b3aa4,0x39cf39de,0x3a223a4f,0x39b039bf,0x39c139f3,0x399139a0,0x395a398e,0x39713981,0x38eb3923,0x39503961,0x387638b1,0x392f3940,0x37f63839,
0xb921b90b,0xb816b7a4,0xb94bb936,0xb89ab859,0xb975b961,0xb917b8d9,0xb99eb98a,0xb98cb953,0xb9c6b9b2,0xb9f9b9c4,0xb9ecb9d9,0xba5dba2c,0xba12b9ff,0xbab7ba8b,0xba36ba24,0xbb07bae1,
0xba3eba53,0xbaf5bb1d,0xba12ba28,0xba9bbaca,0xb9e4b9fb,0xba36ba6a,0xb9b4b9cc,0xb9c6b9ff,0xb983b99c,0xb94bb98a,0xb950b96a,0xb8c8b90b,0xb91cb936,0xb83cb883,0xb8e6b901,0xb750b7e6,
0x38e138c0,0x379e36fc,0x39213901,0x386b381e,0x395e3940,0x38fe38b6,0x399a397c,0x39883944,0x39d339b7,0x3a0539c8,0x3a0a39ef,0x3a773a40,0x3a3e3a24,0x3adc3aab,0x3a703a57,0x3b333b09,
0x3a703a8b,0x3b1c3b47,0x3a363a53,0x3abb3aed,0x39f93a18,0x3a4a3a84,0x39b939d9,0x39ca3a0c,0x39753997,0x393d3985,0x392f3953,0x38a438f2,0x38e6390b,0x38003854,0x389a38c0,0x36a73756,
0xb70db651,0xb4aeb309,0xb83cb7c5,0xb6ebb5d1,0xb8e6b892,0xb880b7fb,0xb983b936,0xb971b8fc,0xba12b9cc,0xba42b9de,0xba91ba53,0xbaefba9d,0xbafebaca,0xbb74bb37,0xbb5abb2e,0xbbcebba6,
0xbb40bb6c,0xbbb2bbd8,0xbad9bb0f,0xbb43bb80,0xba5dba9d,0xbaa6bafa,0xb9cfba18,0xb9e0ba48,0xb92fb981,0xb8f5b96e,0xb880b8d9,0xb7d5b873,0xb788b824,0xb590b6b8,0xb5fab6c3,0xb251b460,
0x367935a2,0x34113197,0x380b374b,0x3684354f,0x38cd386e,0x386637af,0x397e3928,0x396c38ed,0x3a1e39d1,0x3a4e39e2,0x3aa93a66,0x3b043aaf,0x3b1f3ae7,0x3b8c3b4e,0x3b7d3b51,0x3be03bbd,
0x3b613b8d,0x3bc73be8,0x3af53b2e,0x3b5a3b97,0x3a703ab6,0x3ab73b0f,0x39d33a24,0x39e43a53,0x3921397c,0x38e6396a,0x385c38c0,0x37883859,0x370d37e6,0x350e3651,0x3549362e,0x30de3383,
0xb5e2b4f0,0xb2e4b023,0xb7b4b6cf,0xb61db4cc,0xb8b4b849,0xb84cb761,0xb97ab919,0xb967b8de,0xba2ab9d5,0xba59b9e6,0xbac1ba79,0xbb19bac0,0xbb3dbb03,0xbba2bb65,0xbb9cbb70,0xbbefbbd0,
0xbb7fbbaa,0xbbd8bbf4,0xbb10bb4c,0xbb6fbbac,0xba82bacd,0xbac8bb23,0xb9d7ba30,0xb9e8ba5f,0xb912b978,0xb8d7b965,0xb836b8a7,0xb73ab83e,0xb690b783,0xb48ab5e8,0xb496b596,0xaecfb244,
0x3549343b,0x31a42d58,0x37503651,0x35b33447,0x389a3824,0x38313713,0x3975390b,0x396338cf,0x3a3639d9,0x3a6539ea,0x3ad93a8b,0x3b2d3ad0,0x3b5a3b1d,0x3bb53b7a,0x3bb73b8d,0x3bf93be0,
0x3b9a3bc3,0x3be73bfc,0x3b2a3b67,0x3b833bbe,0x3a943ae4,0x3ad93b37,0x39db3a3c,0x39ec3a6a,0x39033973,0x38c83961,0x3811388d,0x36eb3824,0x3611371e,0x3405357e,0x33c034fc,0x2bc03103,
0xb061a8cf,0x25b230ac,0xb549b383,0xb32eae84,0xb816b6c3,0xb750b57e,0xb95eb8c0,0xb94bb883,0xba70b9ef,0xba9bb9ff,0xbb40bae1,0xbb83bb1d,0xbbc7bb8d,0xbbf5bbcc,0xbbffbbed,0xbbeabbff,
0xbbf2bc00,0xbbfebbe3,0xbb96bbcf,0xbbd2bbf9,0xbae9bb49,0xbb25bb8b,0xb9f1ba75,0xba01baa1,0xb8b9b95c,0xb87bb949,0xb69bb809,0xb555b734,0xb2fdb514,0xad71b2bf,0xa376af7e,0x31662966,
0x2e39a052,0xabf2b21f,0x34de3276,0x32512c5e,0x37f63673,0x3718352c,0x395a38b1,0x39473873,0x3a7b39f3,0x3aa63a03,0x3b523af0,0x3b923b2c,0x3bd63b9f,0x3bfb3bd8,0x3c003bf6,0x3bda3bfc,
0x3bfa3bff,0x3bf93bd1,0x3ba73bdd,0x3bdd3bfd,0x3af83b5b,0x3b333b99,0x39f53a80,0x3a053aab,0x38a93957,0x386b3944,0x364b37db,0x350236fc,0x31ee34a8,0x2a9331e2,0xa8062cf4,0xb2d8ad3f,
0xab5c2af8,0x2e843390,0xb472b166,0xb172a86b,0xb7bfb622,0xb6e0b4d8,0xb955b8a2,0xb942b863,0xba86b9f7,0xbab0ba08,0xbb64bb00,0xbba0bb39,0xbbe3bbaf,0xbbffbbe2,0xbbfdbbfd,0xbbc6bbf5,
0xbbffbbfa,0xbbf1bbba,0xbbb7bbe8,0xbbe7bc00,0xbb07bb6c,0xbb40bba6,0xb9f9ba8b,0xba0abab6,0xb89ab953,0xb85cb940,0xb5fab7a4,0xb4aeb6c3,0xb0deb43b,0xa484b103,0x2cf4a8cf,0x34232fc9,
0x2484ae6b,0xb086b47e,0x34053055,0x30931248,0x378835d1,0x36a73484,0x39503892,0x393d3854,0x3a9139fb,0x3abb3a0c,0x3b743b0f,0x3bad3b47,0x3bed3bbe,0x3c003beb,0x3bf63c00,0x3bae3beb,
0x3c003bf0,0x3be53ba0,0x3bc53bf2,0x3bef3c00,0x3b163b7c,0x3b4d3bb3,0x39fd3a96,0x3a0e3ac0,0x388b394e,0x384c393b,0x35a8376c,0x345a368a,0x2f97339c,0xa4203023,0xafe298b6,0xb4d8b128,
0x31c93531,0x355b37e0,0xaf652839,0x9d7f315a,0xb66db42f,0xb584b1b0,0xb939b844,0xb925b803,0xbac5ba10,0xbaecba20,0xbbb9bb53,0xbbdfbb82,0xbbffbbf2,0xbbe3bc00,0xbb91bbde,0xbaf7bb8a,
0xbbd6bb81,0xbb7cbadf,0xbbf5bbfd,0xbc00bbdd,0xbb5abbbe,0xbb88bbe3,0xba12baca,0xba22baf0,0xb83cb936,0xb7f6b923,0xb405b651,0xb15ab567,0x2a61ae84,0x31e22052,0x358a3269,0x381935a8,
0xb309b5e2,0xb5f4b841,0x2da3ac44,0xa5b2b269,0x363433b4,0x35493103,0x39343834,0x392137e6,0x3acf3a14,0x3af53a24,0x3bc43b60,0x3be73b8d,0x3bfb3bf8,0x3bd63bff,0x3b703bce,0x3ac63b6d,
0x3bc53b5f,0x3b5d3aad,0x3bfa3bf9,0x3bff3bcf,0x3b663bc9,0x3b923bea,0x3a163ad4,0x3a263afa,0x382c3931,0x37d5391e,0x335f3617,0x30ac352c,0xad582cc2,0xb2f0a89d,0xb63ab3a8,0xb869b63f,
0x34233690,0x368a3890,0xabc02e6b,0x2a613377,0xb5fab309,0xb50eb055,0xb92fb824,0xb91cb7c5,0xbad9ba18,0xbafeba28,0xbbcebb6c,0xbbedbb97,0xbbf6bbfc,0xbbc7bbfd,0xbb4cbbba,0xba93bb4d,
0xbbafbb38,0xbb3cba77,0xbbfebbf2,0xbbfcbbbf,0xbb72bbd3,0xbb9cbbf0,0xba1abadd,0xba2abb03,0xb81cb92d,0xb7b4b919,0xb2b3b5dc,0xaffbb4f0,0x2f7ea9fd,0x33fd2c12,0x36e53472,0x38b636d4,
0xb4c0b73a,0xb71eb8dc,0x2839b048,0xacf4b441,0x35bf325d,0x34d22f4c,0x392a3813,0x391737a4,0x3ae23a1c,0x3b073a2c,0x3bd73b77,0x3bf33ba1,0x3bee3bff,0x3bb63bfa,0x3b233ba4,0x3a5b3b2a,
0x3b973b0d,0x3b183a3e,0x3c003be9,0x3bf73bad,0x3b7d3bdb,0x3ba63bf5,0x3a1e3ae7,0x3a2e3b0c,0x380b3928,0x37933914,0x320735a2,0x2e9d34b4,0xb0d124e9,0xb484add5,0xb78eb50e,0xb901b767,
0xb97239ba,0x39dc3996,0xb8323ab5,0x3ad0385d,0x3927b9fe,0xba1fb94d,0x37b7bae9,0xbb02b807,0xb8d83a3f,0x3a5e3900,0xb7053b1a,0x3b30375e,0x3887ba7c,0xba99b8b0,0x364ebb46,0xbb5ab6aa,
0xb90039dc,0x3a3f3972,0xad7e3be6,0x3bf83115,0x3807ba99,0xbae9b887,0xabd9bc00,0xbbfca248,0xb5f13b30,0x3b6e3705,0x32a13bed,0x3bd4b04e,0x3365bba0,0xbbc9b4d5,0xb593bbaf,0xbb803475,
0xb88739fe,0x3a99394d,0x35f13bbc,0x3b6eb414,0x3593bb1a,0xbb80b75e,0xb8b0bb02,0xba7c37b7,0xaf0e3bc9,0x3bf43365,0x3a1f39dc,0x3927b972,0xb04ebc00,0xbbed2248,0xbb30b85d,0xb7053ab5,
0xb8073a1f,0x3ae93927,0x39fe3a3f,0x394db900,0x31dbbb80,0xbbddb593,0xbb6eb832,0xb5f13ad0,0x31153c00,0x3be62248,0x3bff32a1,0x28b6bbd4,0xb7b7bb91,0xbb023534,0xbba0304e,0x34d53bed,
0xb7053a3f,0x3b303900,0x3bbc375e,0x3414bb1a,0x2248bbc9,0xbc00b365,0xbbdda8b6,0x31db3bff,0x36aa3bd4,0x3b46b2a1,0x3a7cb64e,0xb8b0bb5a,0xba1fba5e,0xb92738d8,0xb7b739fe,0x3b02394d,
0xb5f13a5e,0x3b6e38d8,0x3bd42bd9,0xb2a1bbfc,0xb115bbf4,0xbbe6af0e,0xb9dc375e,0x39723b1a,0x39273b46,0x3a1fb6aa,0x3475bad0,0xbbafb832,0xbb91b887,0xb5343a99,0x34143c00,0x3bbc2248,
0xb4d53a7c,0x3ba038b0,0x3a3fb593,0xb900bb80,0xb534bc00,0xbb912248,0xb4143ab5,0x3bbc385d,0x3a993a5e,0x3887b8d8,0xb5f1bbfc,0xbb6e2bd9,0xbbffb475,0x28b63baf,0x3ad03a1f,0x3832b927,
0xb3653a99,0x3bc93887,0x36aab996,0xbb46b9ba,0xb7b7bbed,0xbb02304e,0x34d53bfc,0x3ba02bd9,0x3b913927,0x3534ba1f,0xbae9ba3f,0xb8073900,0xbb5a28b6,0x364e3bff,0x3bd43115,0xb2a1bbe6,
0xb1153ab5,0x3be6385d,0xa8b6bb6e,0xbbffb5f1,0xb900bbbc,0xba3f3414,0x3a1f3b30,0x3927b705,0x3bfc375e,0x2bd9bb1a,0xbbedb475,0x304e3baf,0xb9ba3593,0x39963b80,0x3887b832,0xba99bad0,
0xad7e3ad0,0x3bf83832,0xb7b7bbff,0xbb0228b6,0xb9febb6e,0xb94d35f1,0x3bed3887,0x304eba99,0x3bd43414,0xb2a1bbbc,0xb9963534,0x39ba3b91,0xb6aa3900,0x3b463a3f,0xb115bba0,0xbbe6b4d5,
0xa2483ae9,0x3c003807,0xba99bb30,0xb8873705,0xbad0bb02,0xb83237b7,0x3b462d7e,0xb6aabbf8,0x3b1a28b6,0xb75ebbff,0xaf0e3a7c,0x3bf438b0,0xabd93ab5,0x3bfc385d,0xba5ebb5a,0xb8d8364e,
0x2bd93b02,0x3bfc37b7,0xbbedb927,0xb04e3a1f,0xbb6eba7c,0xb5f138b0,0x385db6aa,0xbab5bb46,0x39dcb1db,0xb972bbdd,0x38323c00,0x3ad02248,0x34d53bbc,0x3ba03414,0xbbf4b705,0x2f0e3b30,
0x304e3b1a,0x3bed375e,0xbb91b475,0x35343baf,0xbbd4b9dc,0xb2a13972,0x2248ba7c,0xbc00b8b0,0x3832b64e,0xbad0bb5a,0x3b803a99,0x3593b887,0x39003bfc,0x3a3fabd9,0xb9273414,0x3a1f3bbc,
0x32a13b30,0x3bd43705,0xb996304e,0x39ba3bed,0xbbffb927,0xa8b63a1f,0xb832bbf4,0xbad0af0e,0x3475b8b0,0xbbafba7c,0x3ba03593,0xb4d5bb80,0x3ae93b6e,0x3807b5f1,0x2bd93a99,0x3bfc3887,
0x34753b46,0x3baf36aa,0xb4d53832,0x3ba03ad0,0xbbedb85d,0x304e3ab5,0xbb30bb5a,0xb705364e,0x2248b9fe,0xbc00b94d,0x3887b414,0xba99bbbc,0x3be63a1f,0x3115b927,0x39dc3bf4,0x3972af0e,
0x35933b5a,0x3b80364e,0x31153a99,0x3be63887,0xbba0b705,0x34d53b30,0xbbf4b8d8,0x2f0e3a5e,0xb414bb02,0xbbbcb7b7,0xabd9ba1f,0xbbfcb927,0x3bd43832,0xb2a1bad0,0x3c003972,0xa248b9dc,
0x36aa3b6e,0x3b4635f1,0x38b03bdd,0x3a7c31db,0xbb1ab534,0x375e3b91,0xba3fb04e,0x39003bed,0xb807bbaf,0xbae9b475,0xb94dbbf8,0xb9fead7e,0x3ab53365,0xb85dbbc9,0x39ba28b6,0xb996bbff,
0x37b73b80,0x3b023593,0x3b1a3bc9,0x375eb365,0xba5eb2a1,0x38d83bd4,0xb53435f1,0x3b913b6e,0xb9babbfc,0xb996abd9,0xbbddbae9,0xb1db3807,0x38b0ad7e,0xba7cbbf8,0x28b6b900,0xbbffba3f,
0x385d3b91,0x3ab53534,0x3c003a5e,0x2248b8d8,0xb972ad7e,0x39dc3bf8,0x33653a3f,0x3bc93900,0xbb02bbe6,0xb7b73115,0xbb1ab6aa,0x375e3b46,0x3414b64e,0xbbbcbb5a,0xb94dbbdd,0xb9feb1db,
0x38d83ba0,0x3a5e34d5,0x3b3037b7,0xb705bb02,0xb85d28b6,0x3ab53bff,0x39ba3be6,0x39963115,0xbbc9bb6e,0xb36535f1,0xb6aa31db,0x3b463bdd,0xaf0eb94d,0xbbf4b9fe,0xbbf8bae9,0xad7e3807,
0x394d3baf,0x39fe3475,0x38d82d7e,0xba5ebbf8,0xb64e3115,0x3b5a3be6,0x3bd43b80,0x32a1b593,0xbbffba99,0x28b63887,0x336539ba,0x3bc93996,0xb75ebae9,0xbb1ab807,0xba3fb534,0x39003b91,
0x39ba3bbc,0x39963414,0x31dbb534,0xbbddbb91,0xb3653475,0x3bc93baf,0x3b803927,0xb593ba1f,0xbba0b972,0x34d539dc,0x3a3f3be6,0x39003115,0xb9febbd4,0xb94db2a1,0xb04e35f1,0x3bed3b6e,
0x3a1f3bc9,0x39273365,0xb475b972,0xbbafb9dc,0xabd9364e,0x3bfc3b5a,0x38d831db,0xba5ebbdd,0xbab5b807,0x385d3ae9,0x3c003b30,0x2248b705,0xbb80bbf4,0xb5932f0e,0x38b03b1a,0x3a7c375e,
0x3a7c3bd4,0x38b032a1,0xb972bb5a,0xb9dcb64e,0x2f0e3807,0x3bf43ae9,0x2d7eb534,0xbbf8bb91,0xb94db4d5,0x39fe3ba0,0x3a5e37b7,0xb8d8bb02,0xbc00bb46,0x224836aa,0x3bdd3bc9,0x31dbb365,
0x3ad03bdd,0x383231db,0xbb80bc00,0xb5932248,0x347538d8,0x3baf3a5e,0xb75eb9fe,0xbb1ab94d,0xb705ad7e,0x3b303bf8,0x3414af0e,0xbbbcbbf4,0xbb6eb9dc,0x35f13972,0x3ab538b0,0xb85dba7c,
0x3b1a3be6,0x375e3115,0xbbf4bb46,0x2f0e36aa,0x37053996,0x3b3039ba,0xbae9bbd4,0xb807b2a1,0xb1db304e,0x3bdd3bed,0xb64eb94d,0xbb5ab9fe,0xb9dcb7b7,0x39723b02,0x3365ad7e,0xbbc9bbf8,
0x3b5a3bed,0x364e304e,0xbab5b94d,0x385d39fe,0x38b03a3f,0x3a7c3900,0xbbffbba0,0x28b634d5,0x2d7e3593,0x3bf83b80,0xbb02bbc9,0xb7b7b365,0xb705b1db,0x3b303bdd,0xb807b9ba,0xbae9b996,
0x3b913bf4,0x35342f0e,0xb807b4d5,0x3ae93ba0,0x39ba3ad0,0x39963832,0xba99b972,0x388739dc,0x3593385d,0x3b803ab5,0xbbe6bb6e,0x311535f1,0xad7e304e,0x3bf83bed,0xbbafbbfc,0xb475abd9,
0x3bbc3bf8,0x34142d7e,0xabd92f0e,0x3bfc3bf4,0x3a993b46,0x388736aa,0xb64eb365,0x3b5a3bc9,0x38b039ba,0x3a7c3996,0xb972b85d,0x39dc3ab5,0x34753705,0x3baf3b30,0xbb1aba5e,0x375e38d8,
0x3bdd3bfc,0x31db2bd9,0x364e3807,0x3b5a3ae9,0x3b463ba0,0x36aa34d5,0x31153475,0x3be63baf,0x3a3f3ad0,0x39003832,0xad7e28b6,0x3bf83bff,0x38d83996,0x3a5e39ba,0xb534b2a1,0x3b913bd4,
0x3bf43bff,0x2f0e28b6,0x3a1f3a7c,0x392738b0,0x3bbc3bdd,0x341431db,0x394d39ba,0x39fe3996,0x3b5a3b91,0x364e3534,0x385d38d8,0x3ab53a5e,0x3ad03b1a,0x3832375e,0x36aa37b7,0x3b463b02,
0x3bff3c00,0x28b62248,0x3bc93bd4,0x336532a1,0x3bf83bfc,0x2d7e2bd9,0x3baf3bbc,0x34753414,0x3bed3bf4,0x304e2f0e,0x3b913ba0,0x353434d5,0x3bdd3be6,0x31db3115,0x3b6e3b80,0x35f13593,
0xb5933b6e,0x3b8035f1,0xb1153bdd,0x3be631db,0x34d5bb91,0xbba0b534,0x2f0ebbed,0xbbf4b04e,0xb4143baf,0x3bbc3475,0xabd93bf8,0x3bfc2d7e,0x32a1bbc9,0xbbd4b365,0x2248bbff,0xbc00a8b6,
0x37b73b46,0x3b02b6aa,0x3b1a3832,0x375ebad0,0xb8d8bab5,0xba5e385d,0xbb91b64e,0xb5343b5a,0x39ba39fe,0x3996b94d,0x3bdd3414,0x31dbbbbc,0xba7cb927,0xb8b03a1f,0xbbffaf0e,0xa8b63bf4,
0x3bd43534,0x32a1bb91,0x39bab8d8,0xb996ba5e,0xbbffad7e,0x28b63bf8,0xb8323a3f,0x3ad03900,0x3bafb115,0xb475bbe6,0x34d5bb46,0xbba0b6aa,0xbae9364e,0x38073b5a,0xabd93bdd,0x3bfc31db,
0x3a5eb75e,0xb8d8bb1a,0xb705bbaf,0xbb303475,0xb85d39dc,0x3ab53972,0x39ba3a7c,0x3996b8b0,0x3365bb5a,0xbbc9b64e,0xbb46b887,0xb6aa3a99,0x2f0e3bfc,0x3bf42bd9,0x3bf83414,0x2d7ebbbc,
0x2bd9bbaf,0xbbfcb475,0xbbedad7e,0x304e3bf8,0x35f13be6,0x3b6eb115,0x3ab5b593,0xb85dbb80,0xb9dcba99,0xb9723887,0xb83239ba,0x3ad03996,0x3ba03807,0x34d5bae9,0x2f0ebb91,0xbbf4b534,
0xb9babae9,0xb9963807,0xb1db3b30,0x3bdd3705,0x3bc937b7,0x3365bb02,0xb593bbf8,0xbb802d7e,0xbba028b6,0x34d53bff,0x3a3f3a7c,0x3900b8b0,0x394db85d,0xb9febab5,0xbbedb64e,0xb04e3b5a,
0xbbf8b365,0x2d7e3bc9,0x3b0239dc,0x37b7b972,0x39feb64e,0xb94dbb5a,0xbbedb1db,0x304e3bdd,0xb2a13ae9,0x3bd43807,0x39bab705,0xb996bb30,0xb6aabbf4,0xbb462f0e,0xb1153b1a,0x3be6375e,
0xb8b0385d,0x3a7c3ab5,0x39dcb5f1,0xb972bb6e,0xaf0ebbbc,0xbbf4b414,0xad7e3b30,0x3bf83705,0x39fe3b1a,0x394db75e,0xb8d8bbaf,0xba5e3475,0xbc00b593,0x22483b80,0x3bdd3832,0x31dbbad0,
0x33653bdd,0x3bc931db,0xb6aabc00,0xbb462248,0xbb02ba5e,0xb7b738d8,0x3ba0394d,0x34d5b9fe,0x3b912d7e,0xb534bbf8,0xbae92f0e,0x38073bf4,0xb64e3972,0x3b5a39dc,0x32a1ba7c,0xbbd4b8b0,
0x3b1a3a7c,0x375eb8b0,0xbbf4b593,0x2f0e3b80,0xbb30a248,0x37053c00,0x3807b85d,0xbae9bab5,0x31dbba5e,0xbbddb8d8,0x364e3bfc,0x3b5a2bd9,0x39723baf,0x39dcb475,0xbbc9b927,0xb3653a1f,
0x3b6e304e,0xb5f1bbed,0xb2a139fe,0x3bd4394d,0xb1153a3f,0x3be63900,0xb9dcbba0,0xb97234d5,0xba1fbb80,0xb9273593,0x3baf3365,0xb475bbc9,0x3b9131db,0xb534bbdd,0xb41439ba,0x3bbc3996,
0x3534b900,0xbb91ba3f,0x3ae93b1a,0x3807b75e,0x39ba3bc9,0x3996b365,0xba9928b6,0x38873bff,0xbb80b2a1,0x35933bd4,0xb115bb5a,0xbbe6b64e,0x2d7eba5e,0xbbf8b8d8,0x3baf39fe,0x3475b94d,
0xb807bbf8,0xbae9ad7e,0x39feaf0e,0xb94dbbf4,0x3bdd36aa,0xb1dbbb46,0x35f13bc9,0x3b6e3365,0xb11539ba,0x3be63996,0xbbffb85d,0x28b63ab5,0xbb02bb30,0xb7b73705,0x34d5b8d8,0xbba0ba5e,
0xbbddb9fe,0xb1db394d,0xb64ebbbc,0xbb5ab414,0x36aab75e,0xbb46bb1a,0x3be637b7,0xb115bb02,0x3a3f3bc9,0x3900b365,0xad7e39dc,0x3bf83972,0xba5ea248,0x38d83c00,0xbb91bab5,0xb534385d,
0xba3fa8b6,0x39003bff,0xbbf8b8b0,0x2d7e3a7c,0xb807bbdd,0xbae9b1db,0x2bd9b9ba,0xbbfcb996,0x3b6e3534,0xb5f1bb91,0x3bd43a5e,0x32a1b8d8,0x33653b1a,0x3bc9375e,0xb59337b7,0x3b803b02,
0xa8b63996,0x3bff39ba,0xb365385d,0x3bc93ab5,0xbbf8b9fe,0xad7e394d,0xbbafbae9,0xb4753807,0x304eb900,0xbbedba3f,0x3534b75e,0xbb91bb1a,0x3bdd3a7c,0x31dbb8b0,0x3b6e3b46,0x35f1b6aa,
0x39dc3c00,0x3972a248,0x3ad03bd4,0x3832b2a1,0xb9272bd9,0x3a1f3bfc,0xb7b73414,0x3b023bbc,0xba5ebbf4,0xb8d82f0e,0xbb30bba0,0xb70534d5,0x3887b115,0xba99bbe6,0x364eb593,0xbb5abb80,
0x3bf43972,0xaf0eb9dc,0x3a1f3115,0xb927bbe6,0x34143a99,0x3bbc3887,0x39fe3c00,0x394d2248,0xbb5ab705,0x364e3b30,0xb85d304e,0x3ab53bed,0xb832bba0,0xbad0b4d5,0xbb46bbaf,0xb6aa3475,
0x3887abd9,0xba99bbfc,0xb5f1bae9,0xbb6eb807,0x3b803ba0,0x3593b4d5,0x3a7c3475,0xb8b0bbaf,0xaf0e3832,0x3bf43ad0,0x3a1f3bff,0x392728b6,0xbbedb996,0x304e39ba,0xb70532a1,0x3b303bd4,
0xb414ba1f,0xbbbcb927,0xbbfcba3f,0x2bd93900,0x3a993593,0xb887bb80,0xb64ebad0,0xbb5ab832,0x3a7c3c00,0x38b02248,0x39dc32a1,0xb972bbd4,0xb4753534,0x3baf3b91,0x3b1a3bed,0x375eb04e,
0xbb30bbf4,0xb7052f0e,0xb41434d5,0x3bbc3ba0,0x2248b832,0xbc00bad0,0xbbddb9dc,0x31db3972,0x3b46385d,0xb6aabab5,0xb8b0bb6e,0xba7cb5f1,0x3a1f3bed,0x3927304e,0x37b7abd9,0xbb02bbfc,
0xbb5ab8d8,0x364e3a5e,0x3ab53bfc,0x385d2bd9,0xba7cbbf4,0xb8b0af0e,0xa8b6375e,0x3bff3b1a,0x2d7eb6aa,0xbbf8bb46,0xbb02b832,0x37b73ad0,0x3b303887,0xb705ba99,0xbae9bc00,0xb807a248,
0xb4d53115,0x3ba03be6,0x3a3f36aa,0xb900bb46,0xbb91b996,0x353439ba,0x3bbc3bd4,0x3414b2a1,0xba99bbed,0xb887b04e,0x35f139fe,0x3b6e394d,0xa8b6b7b7,0xbbffbb02,0xb832ad7e,0x3ad03bf8,
0x38323a99,0x3ad03887,0xb593b996,0xbb80b9ba,0xb475304e,0x3baf3bed,0x375e2bd9,0xbb1abbfc,0xbb30b927,0x37053a1f,0x3bbc3a3f,0xb414b900,0xbb6ebbff,0xb5f128b6,0x3ab53be6,0x385d3115,
0x3be63bd4,0x3115b2a1,0xbbffbb5a,0x28b6364e,0x39003ae9,0x3a3f3807,0xba1fbb91,0xb927b534,0xabd934d5,0x3bfc3ba0,0xb04eb7b7,0xbbedbb02,0xb9bab6aa,0x39963b46,0x38873365,0xba99bbc9,
0x3a1f3832,0xb927bad0,0xb47528b6,0x3baf3bff,0x3bfc3b6e,0xabd9b5f1,0xba5eb887,0x38d83a99,0x3ab53bbc,0x385d3414,0xbc00bb91,0x22483534,0x35933900,0x3b803a3f,0xba7cbba0,0xb8b0b4d5,
0x2248b414,0xbc00bbbc,0x3a993b91,0x38873534,0x38323475,0xbad0bbaf,0x36aa3927,0x3b463a1f,0x3b1a39dc,0xb75eb972,0xaf0e3115,0x3bf43be6,0x3bfc3bd4,0x2bd9b2a1,0xb8d8b5f1,0x3a5e3b6e,
0xb9febb02,0xb94db7b7,0x3a5e3927,0xb8d8ba1f,0xb64eb8b0,0xbb5aba7c,0x3bd43b46,0xb2a1b6aa,0x28b6b1db,0xbbffbbdd,0x3bc93c00,0x33652248,0x375e3414,0xbb1abbbc,0x3a3f3b30,0x39003705,
0xbbedbba0,0x304e34d5,0xb534b7b7,0xbb91bb02,0xbbd4bbff,0xb2a1a8b6,0x2248b115,0xbc00bbe6,0xbad0bb6e,0xb832b5f1,0x359331db,0xbb80bbdd,0xb900b9fe,0xba3fb94d,0x39273807,0xba1fbae9,
0xb85db705,0x3ab53b30,0xbc00bbed,0x2248304e,0xb9dcb927,0x39723a1f,0xbbc9bbf4,0xb365af0e,0xbb02ba7c,0x37b738b0,0xbb1abb80,0xb75eb593,0xbbbcbb6e,0x341435f1,0xb9feba99,0xb94db887,
0x34753593,0x3baf3b80,0xb4d5b365,0x3ba03bc9,0x304e32a1,0x3bed3bd4,0xb705b5f1,0x3b303b6e,0xa2482bd9,0x3c003bfc,0xb887b807,0x3a993ae9,0xb115ad7e,0x3be63bf8,0xb972b900,0x39dc3a3f,
0x3b463b5a,0x36aa364e,0x3a7c3a99,0x38b03887,0x3b1a3b30,0x375e3705,0x3a3f3a5e,0x390038d8,0x3ae93b02,0x380737b7,0x39fe3a1f,0x394d3927,0x3ab53ad0,0x385d3832,0x39ba39dc,0x39963972,
0x28b63c00,0x3bffa248,0x33653bd4,0x3bc9b2a1,0xad7ebbfc,0xbbf82bd9,0xb475bbbc,0xbbaf3414,0x304e3bf4,0x3bedaf0e,0x35343ba0,0x3b91b4d5,0xb1dbbbe6,0xbbdd3115,0xb5f1bb80,0xbb6e3593,
0x3bf4a8b6,0xaf0ebbff,0x3a1fb8b0,0xb927ba7c,0xbbbc31db,0x34143bdd,0xb94d3996,0x39fe39ba,0x3b5ab534,0xb64ebb91,0x385dba5e,0xbab5b8d8,0xbad0375e,0x38323b1a,0xb6aa3b02,0x3b4637b7,
0xb1dbbbfc,0xbbdd2bd9,0xbb5ab807,0xb64e3ae9,0x36aa3ba0,0x3b46b4d5,0x3be63475,0x3115bbaf,0xb900bad0,0xba3f3832,0xbbf8a8b6,0x2d7e3bff,0x3a5e3996,0x38d8b9ba,0x3b91b2a1,0xb534bbd4,
0xbbbc2d7e,0x34143bf8,0x2bd93bf4,0x3bfc2f0e,0x3a99b6aa,0xb887bb46,0xb64ebbc9,0xbb5a3365,0xb8b03996,0x3a7c39ba,0x39723ab5,0x39dcb85d,0x3475bb30,0xbbafb705,0xbb1ab8d8,0xb75e3a5e,
0x35343bf4,0x3b91af0e,0x3ae9b4d5,0xb807bba0,0xb996bad0,0xb9ba3832,0xb8873972,0x3a9939dc,0x3b80385d,0x3593bab5,0x3115bb6e,0xbbe6b5f1,0xbbf8b04e,0x2d7e3bed,0x34753bfc,0x3bafabd9,
0x3b5ab04e,0xb64ebbed,0xbab5b9fe,0xb85d394d,0xb8b03900,0x3a7c3a3f,0x3bff34d5,0x28b6bba0,0x2d7ebb80,0xbbf8b593,0xbb023365,0x37b73bc9,0x37053bdd,0x3b30b1db,0x3807b996,0xbae9b9ba,
0xb75ebbe6,0xbb1a3115,0xaf0e3b46,0x3bf436aa,0x3b303996,0x3705b9ba,0xb807bbd4,0xbae932a1,0xbbddb04e,0x31db3bed,0x3b5a394d,0x364eb9fe,0x3972b7b7,0xb9dcbb02,0xbbc9ad7e,0x33653bf8,
0xbad031db,0x38323bdd,0x3b802248,0xb593bc00,0x3475ba5e,0xbbafb8d8,0xb75e394d,0x3b1a39fe,0x37053bf8,0x3b30ad7e,0xb414bbf4,0xbbbcaf0e,0xbb6eb972,0xb5f139dc,0x3ab53a7c,0x385db8b0,
0x38b03bd4,0x3a7cb2a1,0xb9dcbb5a,0xb972364e,0xbbf4b807,0xaf0e3ae9,0x3bf83534,0xad7ebb91,0x39feb4d5,0xb94dbba0,0xb8d837b7,0x3a5e3b02,0xa2483b46,0x3c0036aa,0xb1dbbbc9,0xbbddb365,
0x3a1fb365,0xb927bbc9,0xb47539dc,0x3baf3972,0x2bd93b5a,0x3bfc364e,0xb8d8bbdd,0xba5e31db,0xbab5bae9,0xb85d3807,0x3c003705,0xa248bb30,0x3b802f0e,0xb593bbf4,0xb8b0375e,0x3a7c3b1a,
0xb996bbbc,0xb9ba3414,0x3bdd3534,0xb1dbbb91,0x3bc93475,0xb365bbaf,0xb5933927,0x3b803a1f,0xb4d53972,0x3ba039dc,0xb900bbe6,0xba3f3115,0xb94dbbd4,0xb9fe32a1,0x3bed35f1,0xb04ebb6e,
0xb94d3475,0x39fe3baf,0xb8d8bbf8,0xba5e2d7e,0xb64ebbe6,0xbb5ab115,0x3bd43593,0xb2a1bb80,0x3bff3887,0x28b6ba99,0xb3653996,0x3bc939ba,0xb75e3807,0x3b1a3ae9,0xba3fbb91,0xb9003534,
0x3a5e3ba0,0x38d8b4d5,0xb70537b7,0x3b303b02,0xbab5a8b6,0x385d3bff,0xb996bbe6,0xb9ba3115,0xb365bb6e,0xbbc9b5f1,0x3b4631db,0xb6aabbdd,0x3bf4394d,0x2f0eb9fe,0x2d7e3ae9,0x3bf83807,
0x385db534,0xbab5bb91,0x3c0038d8,0xa248ba5e,0x39723bf8,0x39dcad7e,0xb3653900,0x3bc93a3f,0xbb02b115,0x37b73be6,0xbb1abb46,0xb75e36aa,0xb414bb5a,0xbbbcb64e,0x394db1db,0xb9febbdd,
0xbb02bb80,0xb7b73593,0xb75ebbc9,0xbb1ab365,0x38d8b2a1,0xba5ebbd4,0x3b9135f1,0xb534bb6e,0x39963bfc,0x39baabd9,0x31db3ae9,0x3bdd3807,0xba7cad7e,0x38b03bf8,0xbbffb900,0x28b63a3f,
0xb6aa35f1,0x3b463b6e,0xb8b031db,0x3a7c3bdd,0xbb1abb91,0xb75e3534,0xba3fbbed,0xb900304e,0x3807b475,0xbae9bbaf,0x394dad7e,0xb9febbf8,0x3ab53bc9,0x385db365,0x39ba3bff,0x3996a8b6,
0x3b803b5a,0x3593b64e,0x3be63a99,0x3115b887,0xb4d53705,0x3ba03b30,0xaf0e38d8,0x3bf43a5e,0xbbbcbb02,0xb41437b7,0xbbfcba1f,0xabd93927,0x32a1b832,0xbbd4bad0,0x2248b972,0xbc00b9dc,
0x3475b6aa,0xbbafbb46,0xb4d5bad0,0xbba0b832,0x3bed3ab5,0x304eb85d,0x3b30364e,0xb705bb5a,0x2248394d,0x3c0039fe,0x38873bbc,0x3a993414,0xbbe6b927,0x31153a1f,0xb9dcaf0e,0x39723bf4,
0xbbd4bb30,0xb2a13705,0xb9bab04e,0x39963bed,0xa8b6b927,0xbbffba1f,0xbad0bbf4,0xb8322f0e,0x3baf38b0,0xb475ba7c,0x34d5b593,0xbba0bb80,0x38073b6e,0x3ae935f1,0x3bfc3a99,0x2bd9b887,
0xb04e375e,0x3bed3b1a,0x3b913baf,0x3534b475,0xbbd4b972,0x32a139dc,0x224838b0,0x3c003a7c,0xb832bb5a,0xbad0b64e,0xbb80b887,0x35933a99,0x39002bd9,0xba3fbbfc,0xb927bbbc,0xba1fb414,
0x3bfc3b02,0x2bd9b7b7,0xb04eb927,0xbbedba1f,0x35f13a7c,0x3b6e38b0,0x3ab536aa,0xb85dbb46,0xb972b1db,0x39dc3bdd,0x3ad03c00,0x3832a248,0xbba0bbbc,0xb4d53414,0xaf0e3705,0x3bf43b30,
0xa248b807,0xbc00bae9,0xba99b705,0x38873b30,0x3ad037b7,0xb832bb02,0xbb46bbf8,0xb6aa2d7e,0x3b1a3bff,0x375ea8b6,0xaf0eb8b0,0xbbf4ba7c,0x2bd9385d,0x3bfc3ab5,0x3a5e364e,0xb8d8bb5a,
0xbbf8bad0,0x2d7e3832,0x3b023bff,0x37b728b6,0xb94dbb6e,0xb9feb5f1,0x304e3887,0x3bed3a99,0x32a1b414,0xbbd4bbbc,0xb9bab534,0x39963b91,0x3b463900,0xb6aaba3f,0xbbe6bba0,0xb11534d5,
0x3115385d,0x3be63ab5,0x28b6b5f1,0xbbffbb6e,0xb900b414,0x3a3f3bbc,0x3a1f3705,0xb927bb30,0xbbfcbb1a,0x2bd9375e,0x3bed3baf,0x304eb475,0xb9babb80,0xb996b593,0x38873ad0,0x3a993832,
0x3bc93a99,0xb365b887,0xbb46b996,0x36aa39ba,0x3b023bed,0x37b7304e,0xbba0bbfc,0xb4d52bd9,0x35343927,0x3b913a1f,0xb807ba3f,0xbae9b900,0xb64ea8b6,0x3b5a3bff,0x32a1b115,0xbbd4bbe6,
0xb4d5b8b0,0xbba0ba7c,0x3a3f3b80,0x39003593,0x35342248,0xbb91bc00,0x3414385d,0x3bbc3ab5,0x3a9938d8,0xb887ba5e,0xb5f1abd9,0x3b6e3bfc,0x3bff3baf,0x28b6b475,0xbad0b927,0x38323a1f,
0xbb6eba5e,0x35f138d8,0x32a1abd9,0xbbd4bbfc,0xbbe6bbf4,0xb1152f0e,0x3972375e,0xb9dcbb1a,0xba1fbb46,0xb927b6aa,0x3baf3ad0,0xb475b832,0xb534b887,0xbb91ba99,0x3bbc3c00,0x3414a248,
0x37053900,0x3b303a3f,0xbbbcbb1a,0x3414375e,0x22483365,0x3c003bc9,0xbbddbbff,0xb1db28b6,0xb6aab2a1,0x3b463bd4,0xba7cbb5a,0xb8b0b64e,0xba1fb8d8,0x39273a5e,0xb7b7b94d,0xbb02b9fe,
0x3ae93a1f,0xb807b927,0x394d3a3f,0x39fe3900,0x3bdd3b80,0xb1dbb593,0x35f13832,0x3b6e3ad0,0x3be63c00,0x3115a248,0x28b632a1,0x3bff3bd4,0x3b023b91,0x37b73534,0xb4d5b04e,0x3ba03bed,
0xb887b94d,0xba99b9fe,0x35f13414,0xbb6ebbbc,0xb593b75e,0xbb80bb1a,0x38b037b7,0xba7cbb02,0xaf0eb365,0xbbf4bbc9,0x3a1f3972,0xb927b9dc,0x304e2248,0xbbedbc00,0x3b303ab5,0xb705b85d,
0xba3fb9dc,0x39003972,0xbbf8bbe6,0x2d7e3115,0xbae9ba99,0x38073887,0xbbfcbc00,0xabd92248,0xbb6ebb30,0x35f13705,0xbbd4bbed,0xb2a1b04e,0xbbc9bba0,0x336534d5,0xbb80bbaf,0xb593b475,
0x39723996,0x39dc39ba,0x3832385d,0x3ad03ab5,0x3927394d,0x3a1f39fe,0x37b73807,0x3b023ae9,0x38d83900,0x3a5e3a3f,0x3705375e,0x3b303b1a,0x388738b0,0x3a993a7c,0x364e36aa,0x3b5a3b46,
0x36aa3b5a,0x3b46b64e,0x38b03a99,0x3a7cb887,0xb75ebb30,0xbb1a3705,0xb900ba5e,0xba3f38d8,0x38073b02,0x3ae9b7b7,0x394d3a1f,0x39feb927,0xb85dbad0,0xbab53832,0xb996b9dc,0xb9ba3972,
0x3475bb80,0xbbafb593,0xb4d5bbc9,0xbba03365,0xb04e3bd4,0x3bed32a1,0x37053b6e,0x3b30b5f1,0xa248bbfc,0xbc00abd9,0xb887bae9,0xba993807,0x31153bf8,0x3be6ad7e,0x39723a3f,0x39dcb900,
0xbab53705,0x385d3b30,0xa2483bed,0x3c00304e,0x3972b927,0xb9dcba1f,0xb365bbf4,0xbbc92f0e,0xb7b73a7c,0x3b0238b0,0x375e3b80,0x3b1ab593,0x3414bb6e,0xbbbcb5f1,0xb94dba99,0xb9fe3887,
0x3bed34d5,0x304ebba0,0x3534bb02,0xbb91b7b7,0xbbd428b6,0x32a13bff,0x22483be6,0x3c003115,0x3ad0b5f1,0xb832bb6e,0xb593bbdd,0xbb8031db,0xb900394d,0x3a3f39fe,0x39273ae9,0x3a1fb807,
0xb94dbb02,0xb9fe37b7,0xb8d83927,0x3a5e3a1f,0x3b5a38b0,0x364eba7c,0x32a1bb46,0xbbd4b6aa,0xbbffb1db,0x28b63bdd,0x33653c00,0x3bc9a248,0x3b1ab414,0xb75ebbbc,0xb900bb30,0xba3f3705,
0x22483bbc,0x3c003414,0x3a99b534,0xb887bb91,0xb832bbaf,0xbad03475,0xb6aa3a1f,0x3b463927,0x3b1a3972,0x375eb9dc,0xaf0ebbe6,0xbbf4b115,0xbbfcb2a1,0x2bd93bd4,0x38d83b6e,0x3a5eb5f1,
0x3927b832,0xba1fbad0,0xbbafa8b6,0x34753bff,0xabd93b6e,0x3bfc35f1,0x38d8b887,0xba5eba99,0xb85dbbbc,0xbab53414,0xa2483b91,0x3c003534,0x3b803900,0x3593ba3f,0xb8b0bba0,0xba7c34d5,
0xbbe6b2a1,0x31153bd4,0x3bff364e,0x28b6bb5a,0x3900b807,0xba3fbae9,0xba1f3534,0x39273b91,0x2bd93ba0,0x3bfc34d5,0x304ebb02,0xbbedb7b7,0xb9babb46,0xb99636aa,0x38873bc9,0x3a99b365,
0x3ad03a99,0x3832b887,0xbb80b996,0xb59339ba,0xbbafb04e,0x34753bed,0x3b1aabd9,0xb75ebbfc,0x3705b927,0xbb30ba1f,0xb4143a3f,0x3bbc3900,0x35f13bff,0x3b6e28b6,0xb85dbbe6,0xbab53115,
0xb4d5bbe6,0xbba0b115,0x3a3f3b46,0x3900b6aa,0x3b9139ba,0x3534b996,0xbbbcb2a1,0x34143bd4,0xba99304e,0x38873bed,0x35f1b94d,0xbb6eb9fe,0x28b6bb02,0xbbffb7b7,0x38323bf8,0x3ad0ad7e,
0xb64e38d8,0x3b5a3a5e,0xb85dbbfc,0xbab52bd9,0xb8b0bbf4,0xba7c2f0e,0x3bff375e,0xa8b6bb1a,0x3bf836aa,0xad7ebb46,0xb7b73832,0x3b023ad0,0xb7053887,0x3b303a99,0xb807bc00,0xbae92248,
0x3b302f0e,0xb705bbf4,0x34143ba0,0x3bbc34d5,0x22483ad0,0x3c003832,0xbbddb972,0xb1db39dc,0xbb46bab5,0xb6aa385d,0x38b0b5f1,0xba7cbb6e,0x3a1fb04e,0xb927bbed,0x37b73bfc,0x3b022bd9,
0xbbbcba1f,0xb4143927,0x2bd9ba3f,0xbbfcb900,0x3887b593,0xba99bb80,0x3b5a3ad0,0x364eb832,0x38b03c00,0x3a7ca248,0xb97232a1,0x39dc3bd4,0xbbafb534,0x34753b91,0xb75ebbed,0xbb1ab04e,
0x38873bfc,0x3a992bd9,0xb5f13807,0x3b6e3ae9,0xbb80b4d5,0x35933ba0,0xba7cbbaf,0xb8b03475,0xaf0ebad0,0xbbf4b832,0x3a1fa8b6,0xb927bbff,0x3bed39ba,0x304eb996,0x37053bd4,0x3b3032a1,
0x2f0eb972,0xbbf4b9dc,0x3927b115,0xba1fbbe6,0x3bbc3a99,0x3414b887,0x394d3c00,0x39fea248,0xb64e3705,0x3b5a3b30,0xbab5b04e,0x385d3bed,0xbad0bba0,0xb83234d5,0xb6aabbaf,0xbb46b475,
0xb9dca248,0x39723c00,0xbad0b2a1,0x38323bd4,0xb927bbfc,0xba1fabd9,0xb7b7bbbc,0xbb02b414,0x3a5e2f0e,0xb8d8bbf4,0x3b3034d5,0xb705bba0,0x38873be6,0x3a993115,0x364e3b80,0x3b5a3593,
0x3bff3996,0xa8b6b9ba,0x3bc9385d,0xb365bab5,0x2d7e39fe,0x3bf8394d,0x34753ae9,0x3baf3807,0xbbedb900,0x304e3a3f,0xbb91b75e,0x35343b1a,0xb1dbba7c,0xbbddb8b0,0xb5f1bb46,0xbb6eb6aa,
0xba3fbbff,0xb90028b6,0xbbf8ba7c,0xad7e38b0,0x3807b1db,0xbae9bbdd,0xabd9b996,0xbbfcb9ba,0x3b6e3b91,0x35f1b534,0x3bd438d8,0xb2a1ba5e,0xb365375e,0x3bc93b1a,0x35933b02,0x3b8037b7,
0x31db39fe,0x3bdd394d,0x3b5a3bbc,0x364eb414,0xbb46b75e,0x36aa3b1a,0xb11537b7,0x3be63b02,0xb900bbc9,0xba3fb365,0xbbf8b9dc,0x2d7e3972,0x38d8a248,0xba5ebc00,0xb534bab5,0xbb91b85d,
0x3807ad7e,0xbae9bbf8,0xb9febbf4,0xb94daf0e,0x3bdd3b46,0x31dbb6aa,0x35f1b365,0xbb6ebbc9,0x31153996,0x3be639ba,0x3bff3ab5,0x28b6b85d,0xbb02b705,0x37b73b30,0x34d53a5e,0x3ba038d8,
0xbb91b900,0x35343a3f,0x38073b1a,0x3ae9375e,0xb996bbc9,0xb9bab365,0xb887a8b6,0x3a993bff,0x3593b2a1,0xbb80bbd4,0xbbe6bb5a,0xb115364e,0x3bf83a5e,0xad7eb8d8,0xb475b9fe,0xbbafb94d,
0x3b6e3bed,0x35f1b04e,0xb2a1b94d,0xbbd4b9fe,0x31153900,0x3be63a3f,0x39dc34d5,0xb972bba0,0xba1fb593,0x39273b80,0x3baf3bc9,0x3475b365,0xbb91bbdd,0xb53431db,0x34143996,0x3bbc39ba,
0xb75eba7c,0xbb1ab8b0,0xaf0e3593,0x3bf43b80,0x3705a248,0xbb30bc00,0xbae9b85d,0x38073ab5,0x3bdd3a5e,0xb1dbb8d8,0xbb5abbfc,0xb64e2bd9,0x39dc3baf,0x39723475,0xb365b927,0xbbc9ba1f,
0xb36531db,0x3bc93bdd,0x36aa2248,0xbb46bc00,0xbb02b8d8,0x37b73a5e,0x3ba039fe,0xb4d5b94d,0xbb91bbf8,0xb5342d7e,0x3ae93bf4,0x38072f0e,0xb64eb9dc,0xbb5ab972,0x32a138b0,0x3bd43a7c,
0x3a7c385d,0xb8b0bab5,0xb972b5f1,0x39dc3b6e,0x3bf43bbc,0x2f0eb414,0xbbf8bb30,0x2d7e3705,0x394d3b1a,0x39fe375e,0xba5ebbaf,0xb8d8b475,0xa2483593,0x3c003b80,0xb1dbb832,0xbbddbad0,
0xbbf8bbc9,0xad7e3365,0x3b023972,0xb7b7b9dc,0xb9febb5a,0xb94db64e,0x3bed3bdd,0x304eb1db,0xb2a1b807,0xbbd4bae9,0x39ba3b30,0x39963705,0x36aa2f0e,0xbb46bbf4,0x3115375e,0x3be63b1a,
0x39963ae9,0x39ba3807,0xbbddbb30,0x31db3705,0x336537b7,0x3bc93b02,0xbb80bbf8,0xb593ad7e,0xb4d5a8b6,0x3ba03bff,0xb900ba7c,0xba3fb8b0,0xb9feb85d,0x394d3ab5,0xb04eb64e,0xbbedbb5a,
0xabd9b475,0xbbfcbbaf,0x3bed3bf8,0x304ead7e,0x35f13115,0xbb6ebbe6,0x3ab53b80,0x385d3593,0x39dc3887,0xb972ba99,0x38323996,0x3ad039ba,0x3ba03ae9,0xb4d5b807,0x2f0e3534,0x3bf43b91,
0xb8d8b75e,0x3a5e3b1a,0xbb30bbaf,0xb705b475,0xbab5b9dc,0x385d3972,0xb996ba7c,0xb9bab8b0,0xbbc9bb5a,0x3365364e,0xb6aab887,0xbb46ba99,0xbbf4bbfc,0xaf0e2bd9,0xad7eb414,0xbbf8bbbc,
0x3bd43b91,0xb2a1b534,0x39ba3a5e,0x399638d8,0x3bff3bf8,0x28b6ad7e,0x38323900,0x3ad03a3f,0x3baf3be6,0x34753115,0x34d536aa,0x3ba03b46,0x3ae93b5a,0x3807364e,0x2bd931db,0x3bfc3bdd,
0xbb02bb46,0xb7b7b6aa,0xb75eb832,0xbb1abad0,0xba5ebab5,0xb8d8b85d,0xb534b64e,0xbb91bb5a,0xb996b9fe,0xb9bab94d,0xb1dbb414,0xbbddbbbc,0xb8b0b927,0xba7cba1f,0xa8b6af0e,0xbbffbbf4,
0x359335f1,0x3b803b6e,0x311531db,0x3be63bdd,0x34d53534,0x3ba03b91,0x2f0e304e,0x3bf43bed,0x34143475,0x3bbc3baf,0x2bd92d7e,0x3bfc3bf8,0x32a13365,0x3bd43bc9,0x224828b6,0x3c003bff,
0x40000,0x60002,0xc0008,0xe000a,0x380034,0x3a0036,0x40003c,0x42003e,0x6c0068,0x6e006a,0x740070,0x760072,0xa0009c,0xa2009e,0xa800a4,0xaa00a6,
0xd400d0,0xd600d2,0xdc00d8,0xde00da,0x1080104,0x10a0106,0x110010c,0x112010e,0x13c0138,0x13e013a,0x1440140,0x1460142,0x170016c,0x172016e,0x1780174,0x17a0176,
0x1a401a0,0x1a601a2,0x1ac01a8,0x1ae01aa,0x1d801d4,0x1da01d6,0x1e001dc,0x1e201de,0x20c0208,0x20e020a,0x2140210,0x2160212,0x240023c,0x242023e,0x2480244,0x24a0246,
0x2740270,0x2760272,0x27c0278,0x27e027a,0x2a802a4,0x2aa02a6,0x2b002ac,0x2b202ae,0x2dc02d8,0x2de02da,0x2e402e0,0x2e602e2,0x310030c,0x312030e,0x3180314,0x31a0316,
0x3440340,0x3460342,0x34c0348,0x34e034a,0x3780374,0x37a0376,0x380037c,0x382037e,0x3ac03a8,0x3ae03aa,0x3b403b0,0x3b603b2,0x3e003dc,0x3e203de,0x3e803e4,0x3ea03e6,
0x4140410,0x4160412,0x41c0418,0x41e041a,0x4480444,0x44a0446,0x450044c,0x452044e,0x47c0478,0x47e047a,0x4840480,0x4860482,0x4b004ac,0x4b204ae,0x4b804b4,0x4ba04b6,
0x4e404e0,0x4e604e2,0x4ec04e8,0x4ee04ea,0x5180514,0x51a0516,0x520051c,0x522051e,0x54c0548,0x54e054a,0x5540550,0x5560552,0x580057c,0x582057e,0x5880584,0x58a0586,
0x5b405b0,0x5b605b2,0x5bc05b8,0x5be05ba,0x5e805e4,0x5ea05e6,0x5f005ec,0x5f205ee,0x61c0618,0x61e061a,0x6240620,0x6260622,0x650064c,0x652064e,0x6580654,0x65a0656,
0x140010,0x160012,0x120010,0x440012,0x480044,0x4a0046,0x460044,0x780046,0x7c0078,0x7e007a,0x7a0078,0xac007a,0xb000ac,0xb200ae,0xae00ac,0xe000ae,
0xe400e0,0xe600e2,0xe200e0,0x11400e2,0x1180114,0x11a0116,0x1160114,0x1480116,0x14c0148,0x14e014a,0x14a0148,0x17c014a,0x180017c,0x182017e,0x17e017c,0x1b0017e,
0x1b401b0,0x1b601b2,0x1b201b0,0x1e401b2,0x1e801e4,0x1ea01e6,0x1e601e4,0x21801e6,0x21c0218,0x21e021a,0x21a0218,0x24c021a,0x250024c,0x252024e,0x24e024c,0x280024e,
0x2840280,0x2860282,0x2820280,0x2b40282,0x2b802b4,0x2ba02b6,0x2b602b4,0x2e802b6,0x2ec02e8,0x2ee02ea,0x2ea02e8,0x31c02ea,0x320031c,0x322031e,0x31e031c,0x350031e,
0x3540350,0x3560352,0x3520350,0x3840352,0x3880384,0x38a0386,0x3860384,0x3b80386,0x3bc03b8,0x3be03ba,0x3ba03b8,0x3ec03ba,0x3f003ec,0x3f203ee,0x3ee03ec,0x42003ee,
0x4240420,0x4260422,0x4220420,0x4540422,0x4580454,0x45a0456,0x4560454,0x4880456,0x48c0488,0x48e048a,0x48a0488,0x4bc048a,0x4c004bc,0x4c204be,0x4be04bc,0x4f004be,
0x4f404f0,0x4f604f2,0x4f204f0,0x52404f2,0x5280524,0x52a0526,0x5260524,0x5580526,0x55c0558,0x55e055a,0x55a0558,0x58c055a,0x590058c,0x592058e,0x58e058c,0x5c0058e,
0x5c405c0,0x5c605c2,0x5c205c0,0x5f405c2,0x5f805f4,0x5fa05f6,0x5f605f4,0x62805f6,0x62c0628,0x62e062a,0x62a0628,0x65c062a,0x660065c,0x662065e,0x65e065c,0x18065e,
0x180018,0x4c001a,0x1a0018,0x4c001a,0x4c004c,0x80004e,0x4e004c,0x80004e,0x800080,0xb40082,0x820080,0xb40082,0xb400b4,0xe800b6,0xb600b4,0xe800b6,
0xe800e8,0x11c00ea,0xea00e8,0x11c00ea,0x11c011c,0x150011e,0x11e011c,0x150011e,0x1500150,0x1840152,0x1520150,0x1840152,0x1840184,0x1b80186,0x1860184,0x1b80186,
0x1b801b8,0x1ec01ba,0x1ba01b8,0x1ec01ba,0x1ec01ec,0x22001ee,0x1ee01ec,0x22001ee,0x2200220,0x2540222,0x2220220,0x2540222,0x2540254,0x2880256,0x2560254,0x2880256,
0x2880288,0x2bc028a,0x28a0288,0x2bc028a,0x2bc02bc,0x2f002be,0x2be02bc,0x2f002be,0x2f002f0,0x32402f2,0x2f202f0,0x32402f2,0x3240324,0x3580326,0x3260324,0x3580326,
0x3580358,0x38c035a,0x35a0358,0x38c035a,0x38c038c,0x3c0038e,0x38e038c,0x3c0038e,0x3c003c0,0x3f403c2,0x3c203c0,0x3f403c2,0x3f403f4,0x42803f6,0x3f603f4,0x42803f6,
0x4280428,0x45c042a,0x42a0428,0x45c042a,0x45c045c,0x490045e,0x45e045c,0x490045e,0x4900490,0x4c40492,0x4920490,0x4c40492,0x4c404c4,0x4f804c6,0x4c604c4,0x4f804c6,
0x4f804f8,0x52c04fa,0x4fa04f8,0x52c04fa,0x52c052c,0x560052e,0x52e052c,0x560052e,0x5600560,0x5940562,0x5620560,0x5940562,0x5940594,0x5c80596,0x5960594,0x5c80596,
0x5c805c8,0x5fc05ca,0x5ca05c8,0x5fc05ca,0x5fc05fc,0x63005fe,0x5fe05fc,0x63005fe,0x6300630,0x6640632,0x6320630,0x6640632,0x6640664,0x1c0666,0x6660664,0x1c0666,
0x1c001c,0x50001e,0x1e001c,0x50001e,0x500050,0x840052,0x520050,0x840052,0x840084,0xb80086,0x860084,0xb80086,0xb800b8,0xec00ba,0xba00b8,0xec00ba,
0xec00ec,0x12000ee,0xee00ec,0x12000ee,0x1200120,0x1540122,0x1220120,0x1540122,0x1540154,0x1880156,0x1560154,0x1880156,0x1880188,0x1bc018a,0x18a0188,0x1bc018a,
0x1bc01bc,0x1f001be,0x1be01bc,0x1f001be,0x1f001f0,0x22401f2,0x1f201f0,0x22401f2,0x2240224,0x2580226,0x2260224,0x2580226,0x2580258,0x28c025a,0x25a0258,0x28c025a,
0x28c028c,0x2c0028e,0x28e028c,0x2c0028e,0x2c002c0,0x2f402c2,0x2c202c0,0x2f402c2,0x2f402f4,0x32802f6,0x2f602f4,0x32802f6,0x3280328,0x35c032a,0x32a0328,0x35c032a,
0x35c035c,0x390035e,0x35e035c,0x390035e,0x3900390,0x3c40392,0x3920390,0x3c40392,0x3c403c4,0x3f803c6,0x3c603c4,0x3f803c6,0x3f803f8,0x42c03fa,0x3fa03f8,0x42c03fa,
0x42c042c,0x460042e,0x42e042c,0x460042e,0x4600460,0x4940462,0x4620460,0x4940462,0x4940494,0x4c80496,0x4960494,0x4c80496,0x4c804c8,0x4fc04ca,0x4ca04c8,0x4fc04ca,
0x4fc04fc,0x53004fe,0x4fe04fc,0x53004fe,0x5300530,0x5640532,0x5320530,0x5640532,0x5640564,0x5980566,0x5660564,0x5980566,0x5980598,0x5cc059a,0x59a0598,0x5cc059a,
0x5cc05cc,0x60005ce,0x5ce05cc,0x60005ce,0x6000600,0x6340602,0x6020600,0x6340602,0x6340634,0x6680636,0x6360634,0x6680636,0x6680668,0x20066a,0x66a0668,0x20066a,
0x5d605d6,0x60a05d6,0x5d605d6,0x60a060a,0x60a060a,0x63e063e,0x60a060a,0x63e063e,0x63e063e,0x672063e,0x63e063e,0x6720672,0x6720672,0x280028,0x6720672,0x280028,
0x5060506,0x53a0506,0x5060506,0x53a053a,0x53a053a,0x56e056e,0x53a053a,0x56e056e,0x56e056e,0x5a2056e,0x56e056e,0x5a205a2,0x5a205a2,0x5d605d6,0x5a205a2,0x5d605d6,
0x4360436,0x46a0436,0x4360436,0x46a046a,0x46a046a,0x49e049e,0x46a046a,0x49e049e,0x49e049e,0x4d2049e,0x49e049e,0x4d204d2,0x4d204d2,0x5060506,0x4d204d2,0x5060506,
0x3660366,0x39a0366,0x3660366,0x39a039a,0x39a039a,0x3ce03ce,0x39a039a,0x3ce03ce,0x3ce03ce,0x40203ce,0x3ce03ce,0x4020402,0x4020402,0x4360436,0x4020402,0x4360436,
0x2960296,0x2ca0296,0x2960296,0x2ca02ca,0x2ca02ca,0x2fe02fe,0x2ca02ca,0x2fe02fe,0x2fe02fe,0x33202fe,0x2fe02fe,0x3320332,0x3320332,0x3660366,0x3320332,0x3660366,
0x1c601c6,0x1fa01c6,0x1c601c6,0x1fa01fa,0x1fa01fa,0x22e022e,0x1fa01fa,0x22e022e,0x22e022e,0x262022e,0x22e022e,0x2620262,0x2620262,0x2960296,0x2620262,0x2960296,
0xf600f6,0x12a00f6,0xf600f6,0x12a012a,0x12a012a,0x15e015e,0x12a012a,0x15e015e,0x15e015e,0x192015e,0x15e015e,0x1920192,0x1920192,0x1c601c6,0x1920192,0x1c601c6,
0x260026,0x5a0026,0x260026,0x5a005a,0x5a005a,0x8e008e,0x5a005a,0x8e008e,0x8e008e,0xc2008e,0x8e008e,0xc200c2,0xc200c2,0xf600f6,0xc200c2,0xf600f6,
0x5d405d4,0x60805d4,0x5d405d4,0x6080608,0x6080608,0x63c063c,0x6080608,0x63c063c,0x63c063c,0x670063c,0x63c063c,0x6700670,0x6700670,0x260026,0x6700670,0x260026,
0x5040504,0x5380504,0x5040504,0x5380538,0x5380538,0x56c056c,0x5380538,0x56c056c,0x56c056c,0x5a0056c,0x56c056c,0x5a005a0,0x5a005a0,0x5d405d4,0x5a005a0,0x5d405d4,
0x4340434,0x4680434,0x4340434,0x4680468,0x4680468,0x49c049c,0x4680468,0x49c049c,0x49c049c,0x4d0049c,0x49c049c,0x4d004d0,0x4d004d0,0x5040504,0x4d004d0,0x5040504,
0x3640364,0x3980364,0x3640364,0x3980398,0x3980398,0x3cc03cc,0x3980398,0x3cc03cc,0x3cc03cc,0x40003cc,0x3cc03cc,0x4000400,0x4000400,0x4340434,0x4000400,0x4340434,
0x2940294,0x2c80294,0x2940294,0x2c802c8,0x2c802c8,0x2fc02fc,0x2c802c8,0x2fc02fc,0x2fc02fc,0x33002fc,0x2fc02fc,0x3300330,0x3300330,0x3640364,0x3300330,0x3640364,
0x1c401c4,0x1f801c4,0x1c401c4,0x1f801f8,0x1f801f8,0x22c022c,0x1f801f8,0x22c022c,0x22c022c,0x260022c,0x22c022c,0x2600260,0x2600260,0x2940294,0x2600260,0x2940294,
0xf400f4,0x12800f4,0xf400f4,0x1280128,0x1280128,0x15c015c,0x1280128,0x15c015c,0x15c015c,0x190015c,0x15c015c,0x1900190,0x1900190,0x1c401c4,0x1900190,0x1c401c4,
0x240024,0x580024,0x240024,0x580058,0x580058,0x8c008c,0x580058,0x8c008c,0x8c008c,0xc0008c,0x8c008c,0xc000c0,0xc000c0,0xf400f4,0xc000c0,0xf400f4,
0x5d205d2,0x60605d2,0x5d205d2,0x6060606,0x6060606,0x63a063a,0x6060606,0x63a063a,0x63a063a,0x66e063a,0x63a063a,0x66e066e,0x66e066e,0x240024,0x66e066e,0x240024,
0x5020502,0x5360502,0x5020502,0x5360536,0x5360536,0x56a056a,0x5360536,0x56a056a,0x56a056a,0x59e056a,0x56a056a,0x59e059e,0x59e059e,0x5d205d2,0x59e059e,0x5d205d2,
0x4320432,0x4660432,0x4320432,0x4660466,0x4660466,0x49a049a,0x4660466,0x49a049a,0x49a049a,0x4ce049a,0x49a049a,0x4ce04ce,0x4ce04ce,0x5020502,0x4ce04ce,0x5020502,
0x3620362,0x3960362,0x3620362,0x3960396,0x3960396,0x3ca03ca,0x3960396,0x3ca03ca,0x3ca03ca,0x3fe03ca,0x3ca03ca,0x3fe03fe,0x3fe03fe,0x4320432,0x3fe03fe,0x4320432,
0x2920292,0x2c60292,0x2920292,0x2c602c6,0x2c602c6,0x2fa02fa,0x2c602c6,0x2fa02fa,0x2fa02fa,0x32e02fa,0x2fa02fa,0x32e032e,0x32e032e,0x3620362,0x32e032e,0x3620362,
0x1c201c2,0x1f601c2,0x1c201c2,0x1f601f6,0x1f601f6,0x22a022a,0x1f601f6,0x22a022a,0x22a022a,0x25e022a,0x22a022a,0x25e025e,0x25e025e,0x2920292,0x25e025e,0x2920292,
0xf200f2,0x12600f2,0xf200f2,0x1260126,0x1260126,0x15a015a,0x1260126,0x15a015a,0x15a015a,0x18e015a,0x15a015a,0x18e018e,0x18e018e,0x1c201c2,0x18e018e,0x1c201c2,
0x220022,0x560022,0x220022,0x560056,0x560056,0x8a008a,0x560056,0x8a008a,0x8a008a,0xbe008a,0x8a008a,0xbe00be,0xbe00be,0xf200f2,0xbe00be,0xf200f2,
0x5d005d0,0x60405d0,0x5d005d0,0x6040604,0x6040604,0x6380638,0x6040604,0x6380638,0x6380638,0x66c0638,0x6380638,0x66c066c,0x66c066c,0x220022,0x66c066c,0x220022,
0x5000500,0x5340500,0x5000500,0x5340534,0x5340534,0x5680568,0x5340534,0x5680568,0x5680568,0x59c0568,0x5680568,0x59c059c,0x59c059c,0x5d005d0,0x59c059c,0x5d005d0,
0x4300430,0x4640430,0x4300430,0x4640464,0x4640464,0x4980498,0x4640464,0x4980498,0x4980498,0x4cc0498,0x4980498,0x4cc04cc,0x4cc04cc,0x5000500,0x4cc04cc,0x5000500,
0x3600360,0x3940360,0x3600360,0x3940394,0x3940394,0x3c803c8,0x3940394,0x3c803c8,0x3c803c8,0x3fc03c8,0x3c803c8,0x3fc03fc,0x3fc03fc,0x4300430,0x3fc03fc,0x4300430,
0x2900290,0x2c40290,0x2900290,0x2c402c4,0x2c402c4,0x2f802f8,0x2c402c4,0x2f802f8,0x2f802f8,0x32c02f8,0x2f802f8,0x32c032c,0x32c032c,0x3600360,0x32c032c,0x3600360,
0x1c001c0,0x1f401c0,0x1c001c0,0x1f401f4,0x1f401f4,0x2280228,0x1f401f4,0x2280228,0x2280228,0x25c0228,0x2280228,0x25c025c,0x25c025c,0x2900290,0x25c025c,0x2900290,
0xf000f0,0x12400f0,0xf000f0,0x1240124,0x1240124,0x1580158,0x1240124,0x1580158,0x1580158,0x18c0158,0x1580158,0x18c018c,0x18c018c,0x1c001c0,0x18c018c,0x1c001c0,
0x200020,0x540020,0x200020,0x540054,0x540054,0x880088,0x540054,0x880088,0x880088,0xbc0088,0x880088,0xbc00bc,0xbc00bc,0xf000f0,0xbc00bc,0xf000f0,
0x30003000,0x30003000,0x30003000,0x30003000,0x30003000,0x30003000,0x30003000,0x30003000,0x0,0x0,0x0,0x0,0x0,0x0,0x0,0x0,
0x30003000,0x30003000,0x30003000,0x30003000,0x30003000,0x30003000,0x30003000,0x30003000,0x0,0x0,0x0,0x0,0x0,0x0,0x0,0x0,
0x2a1f2da8,0xaf64ada8,0xaa1fada8,0x2f642da8,0x2f643000,0xaa1f0000,0xaf64b000,0x2a1f8000,0x2f642da8,0x2a1f2da8,0xaf64ada8,0xaa1fada8,0x2a1f0000,0x2f643000,0xaa1f0000,0xaf64b000,
0x263e2c72,0xafd9aea7,0xa63eac72,0x2fd92ea7,0x2ea72fd9,0xac72a63e,0xaea7afd9,0x2c72263e,0x2fd92ea7,0x263e2c72,0xafd9aea7,0xa63eac72,0x2c72263e,0x2ea72fd9,0xac72a63e,0xaea7afd9,
0x2da80000,0xada80000,0x2da88000,0xada80000,0x2da83000,0xada8b000,0x2da83000,0xada8b000,0x2da83000,0xada8b000,0x2da83000,0xada8b000,0xada80000,0x2da88000,0xada80000,0x2da88000,
0x2f642a1f,0xaf64aa1f,0x2f642a1f,0xaf64aa1f,0x2a1f2f64,0xaa1faf64,0x2a1f2f64,0xaa1faf64,0x2a1f2f64,0xaa1faf64,0x2a1f2f64,0xaa1faf64,0xaf64aa1f,0x2f642a1f,0xaf64aa1f,0x2f642a1f,
0xaa1f2da8,0x2f642da8,0x2a1fada8,0xaf64ada8,0x2f640000,0xaa1fb000,0xaf640000,0x2a1f3000,0xaf64ada8,0xaa1f2da8,0x2f642da8,0x2a1fada8,0x2a1f3000,0x2f648000,0xaa1fb000,0xaf640000,
0xaea7263e,0x2c722fd9,0x2ea7a63e,0xac72afd9,0x2fd92c72,0x263eaea7,0xafd9ac72,0xa63e2ea7,0xac72afd9,0xaea7263e,0x2c722fd9,0x2ea7a63e,0xa63e2ea7,0x2fd92c72,0x263eaea7,0xafd9ac72,
0xada82da8,0xada82da8,0xada82da8,0xada82da8,0x2da8ada8,0x2da8ada8,0x2da8ada8,0x2da8ada8,0x2da82da8,0x2da82da8,0x2da82da8,0x2da82da8,0xada8ada8,0xada8ada8,0xada8ada8,0xada8ada8,
0x3000,0x3000,0x3000,0x80003000,0x8000b000,0x8000b000,0x8000b000,0x8000b000,0x30000000,0x30008000,0x30008000,0x30008000,0xb0000000,0xb0000000,0xb0000000,0xb0000000,
0x2ea7263e,0xac722fd9,0xaea7a63e,0x2c72afd9,0xafd92c72,0xa63eaea7,0x2fd9ac72,0x263e2ea7,0x2c72afd9,0x2ea7263e,0xac722fd9,0xaea7a63e,0x263e2ea7,0xafd92c72,0xa63eaea7,0x2fd9ac72,
0x2f64ada8,0x2a1f2da8,0xaf642da8,0xaa1fada8,0xaa1f3000,0xaf640000,0x2a1fb000,0x2f648000,0xaa1fada8,0x2f64ada8,0x2a1f2da8,0xaf642da8,0x2f640000,0xaa1f3000,0xaf640000,0x2a1fb000,
0xaa1f2f64,0x2a1faf64,0xaa1f2f64,0x2a1faf64,0x2f64aa1f,0xaf642a1f,0x2f64aa1f,0xaf642a1f,0xaf642a1f,0x2f64aa1f,0xaf642a1f,0x2f64aa1f,0xaa1f2f64,0x2a1faf64,0xaa1f2f64,0x2a1faf64,
0x2da80000,0xada80000,0x2da88000,0xada80000,0x2da8b000,0xada83000,0x2da8b000,0xada83000,0xada83000,0x2da8b000,0xada83000,0x2da8b000,0x2da88000,0xada80000,0x2da88000,0xada88000,
0xa63e2c72,0x2fd9aea7,0x263eac72,0xafd92ea7,0xaea72fd9,0x2c72a63e,0x2ea7afd9,0xac72263e,0xafd92ea7,0xa63e2c72,0x2fd9aea7,0x263eac72,0xac72263e,0xaea72fd9,0x2c72a63e,0x2ea7afd9,
0x2f64ada8,0x2a1fada8,0xaf642da8,0xaa1f2da8,0x2a1f0000,0x2f64b000,0xaa1f0000,0xaf643000,0xaa1f2da8,0x2f64ada8,0x2a1fada8,0xaf642da8,0xaf643000,0x2a1f8000,0x2f64b000,0xaa1f8000,
0xb0003000,0xb0003000,0xb0003000,0xb0003000,0xb0003000,0xb0003000,0xb0003000,0xb0003000,0x0,0x8000,0x8000,0x80008000,0x8000,0x8000,0x8000,0x8000,
0x80000000,0x80000000,0x80008000,0x80008000,0x80000000,0x80008000,0x80008000,0x80008000,0xb0003000,0xb0003000,0xb0003000,0xb0003000,0xb0003000,0xb0003000,0xb0003000,0xb0003000,
0xaa1f2da8,0x2f64ada8,0x2a1fada8,0xaf642da8,0xaf643000,0x2a1f0000,0x2f64b000,0xaa1f8000,0xaf642da8,0xaa1f2da8,0x2f64ada8,0x2a1fada8,0xaa1f0000,0xaf643000,0x2a1f0000,0x2f64b000,
0x2fd9aea7,0x263eac72,0xafd92ea7,0xa63e2c72,0x2c72a63e,0x2ea7afd9,0xac72263e,0xaea72fd9,0xa63e2c72,0x2fd9aea7,0x263eac72,0xafd92ea7,0xaea72fd9,0x2c72a63e,0x2ea7afd9,0xac72263e,
0xada80000,0x2da80000,0xada88000,0x2da80000,0xada83000,0x2da8b000,0xada83000,0x2da8b000,0xada83000,0x2da8b000,0xada83000,0x2da8b000,0x2da80000,0xada88000,0x2da88000,0xada88000,
0xaa1f2f64,0x2a1faf64,0xaa1f2f64,0x2a1faf64,0x2f64aa1f,0xaf642a1f,0x2f64aa1f,0xaf642a1f,0x2f64aa1f,0xaf642a1f,0x2f64aa1f,0xaf642a1f,0x2a1faf64,0xaa1f2f64,0x2a1faf64,0xaa1f2f64,
0x2a1f2da8,0xaf642da8,0xaa1fada8,0x2f64ada8,0xaf640000,0x2a1fb000,0x2f640000,0xaa1f3000,0x2f64ada8,0x2a1f2da8,0xaf642da8,0xaa1fada8,0xaa1f3000,0xaf648000,0x2a1fb000,0x2f640000,
0x2c72afd9,0x2ea7263e,0xac722fd9,0xaea7a63e,0x263e2ea7,0xafd92c72,0xa63eaea7,0x2fd9ac72,0xaea7a63e,0x2c72afd9,0x2ea7263e,0xac722fd9,0x2fd9ac72,0x263e2ea7,0xafd92c72,0xa63eaea7,
0x2da8ada8,0x2da8ada8,0x2da8ada8,0x2da8ada8,0xada82da8,0xada82da8,0xada82da8,0xada82da8,0x2da82da8,0x2da82da8,0x2da82da8,0x2da82da8,0xada8ada8,0xada8ada8,0xada8ada8,0xada8ada8,
0x80003000,0x80003000,0x80003000,0x3000,0xb000,0x8000b000,0xb000,0xb000,0xb0000000,0xb0008000,0xb0008000,0xb0008000,0x30000000,0x30000000,0x30000000,0x30008000,
0x2c722fd9,0x2ea7a63e,0xac72afd9,0xaea7263e,0x263eaea7,0xafd9ac72,0xa63e2ea7,0x2fd92c72,0xaea7263e,0x2c722fd9,0x2ea7a63e,0xac72afd9,0x2fd92c72,0x263eaea7,0xafd9ac72,0xa63e2ea7,
0xaf64ada8,0xaa1f2da8,0x2f642da8,0x2a1fada8,0x2a1f3000,0x2f648000,0xaa1fb000,0xaf648000,0x2a1fada8,0xaf64ada8,0xaa1f2da8,0x2f642da8,0xaf640000,0x2a1f3000,0x2f648000,0xaa1fb000,
0x2f642a1f,0xaf64aa1f,0x2f642a1f,0xaf64aa1f,0x2a1f2f64,0xaa1faf64,0x2a1f2f64,0xaa1faf64,0xaa1faf64,0x2a1f2f64,0xaa1faf64,0x2a1f2f64,0x2f642a1f,0xaf64aa1f,0x2f642a1f,0xaf64aa1f,
0xada80000,0x2da80000,0xada88000,0x2da88000,0xada8b000,0x2da83000,0xada8b000,0x2da83000,0x2da83000,0xada8b000,0x2da83000,0xada8b000,0xada88000,0x2da88000,0xada88000,0x2da80000,
0x2fd92ea7,0x263e2c72,0xafd9aea7,0xa63eac72,0x2c72263e,0x2ea72fd9,0xac72a63e,0xaea7afd9,0xa63eac72,0x2fd92ea7,0x263e2c72,0xafd9aea7,0xaea7afd9,0x2c72263e,0x2ea72fd9,0xac72a63e,
0xaf64ada8,0xaa1fada8,0x2f642da8,0x2a1f2da8,0xaa1f0000,0xaf64b000,0x2a1f0000,0x2f643000,0x2a1f2da8,0xaf64ada8,0xaa1fada8,0x2f642da8,0x2f643000,0xaa1f8000,0xaf64b000,0x2a1f0000,
0x80008000,0x80008000,0x80008000,0x80008000,0x80008000,0x80008000,0x80008000,0x80008000,0x30003000,0x30003000,0x30003000,0x30003000,0x30003000,0x30003000,0x30003000,0x30003000,
0x80008000,0x80008000,0x80008000,0x80008000,0x80008000,0x80008000,0x80008000,0x80008000,0x30003000,0x30003000,0x30003000,0x30003000,0x30003000,0x30003000,0x30003000,0x30003000,
0xaf64ada8,0xaa1fada8,0x2f642da8,0x2a1f2da8,0xaa1f8000,0xaf64b000,0x2a1f8000,0x2f643000,0x2a1f2da8,0xaf64ada8,0xaa1fada8,0x2f642da8,0x2f643000,0xaa1f0000,0xaf64b000,0x2a1f8000,
0xafd9aea7,0xa63eac72,0x2fd92ea7,0x263e2c72,0xac72a63e,0xaea7afd9,0x2c72263e,0x2ea72fd9,0x263e2c72,0xafd9aea7,0xa63eac72,0x2fd92ea7,0x2ea72fd9,0xac72a63e,0xaea7afd9,0x2c72263e,
0x2da83000,0xada8b000,0x2da83000,0xada8b000,0xada80000,0x2da88000,0xada80000,0x2da88000,0xada88000,0x2da88000,0xada80000,0x2da88000,0xada8b000,0x2da83000,0xada8b000,0x2da83000,
0x2a1f2f64,0xaa1faf64,0x2a1f2f64,0xaa1faf64,0xaf64aa1f,0x2f642a1f,0xaf64aa1f,0x2f642a1f,0xaf64aa1f,0x2f642a1f,0xaf64aa1f,0x2f642a1f,0xaa1faf64,0x2a1f2f64,0xaa1faf64,0x2a1f2f64,
0xaf64ada8,0xaa1f2da8,0x2f642da8,0x2a1fada8,0x2a1f3000,0x2f648000,0xaa1fb000,0xaf640000,0x2a1fada8,0xaf64ada8,0xaa1f2da8,0x2f642da8,0xaf648000,0x2a1f3000,0x2f648000,0xaa1fb000,
0xac72afd9,0xaea7263e,0x2c722fd9,0x2ea7a63e,0xa63e2ea7,0x2fd92c72,0x263eaea7,0xafd9ac72,0x2ea7a63e,0xac72afd9,0xaea7263e,0x2c722fd9,0xafd9ac72,0xa63e2ea7,0x2fd92c72,0x263eaea7,
0xada8ada8,0xada8ada8,0xada8ada8,0xada8ada8,0x2da82da8,0x2da82da8,0x2da82da8,0x2da82da8,0xada82da8,0xada82da8,0xada82da8,0xada82da8,0x2da8ada8,0x2da8ada8,0x2da8ada8,0x2da8ada8,
0xb0008000,0xb0000000,0xb0000000,0xb0000000,0x30008000,0x30008000,0x30008000,0x30008000,0x3000,0x3000,0x3000,0x80003000,0x8000b000,0x8000b000,0x8000b000,0x8000b000,
0xac722fd9,0xaea7a63e,0x2c72afd9,0x2ea7263e,0xa63eaea7,0x2fd9ac72,0x263e2ea7,0xafd92c72,0x2ea7263e,0xac722fd9,0xaea7a63e,0x2c72afd9,0xafd92c72,0xa63eaea7,0x2fd9ac72,0x263e2ea7,
0x2a1f2da8,0xaf642da8,0xaa1fada8,0x2f64ada8,0xaf648000,0x2a1fb000,0x2f648000,0xaa1f3000,0x2f64ada8,0x2a1f2da8,0xaf642da8,0xaa1fada8,0xaa1f3000,0xaf640000,0x2a1fb000,0x2f648000,
0xaf642a1f,0x2f64aa1f,0xaf642a1f,0x2f64aa1f,0xaa1f2f64,0x2a1faf64,0xaa1f2f64,0x2a1faf64,0x2a1faf64,0xaa1f2f64,0x2a1faf64,0xaa1f2f64,0xaf642a1f,0x2f64aa1f,0xaf642a1f,0x2f64aa1f,
0xada83000,0x2da8b000,0xada83000,0x2da8b000,0x2da88000,0xada80000,0x2da88000,0xada88000,0xada88000,0x2da88000,0xada80000,0x2da88000,0xada83000,0x2da8b000,0xada83000,0x2da8b000,
0xafd92ea7,0xa63e2c72,0x2fd9aea7,0x263eac72,0xac72263e,0xaea72fd9,0x2c72a63e,0x2ea7afd9,0x263eac72,0xafd92ea7,0xa63e2c72,0x2fd9aea7,0x2ea7afd9,0xac72263e,0xaea72fd9,0x2c72a63e,
0xaa1f2da8,0x2f64ada8,0x2a1fada8,0xaf642da8,0xaf643000,0x2a1f8000,0x2f64b000,0xaa1f8000,0xaf642da8,0xaa1f2da8,0x2f64ada8,0x2a1fada8,0xaa1f8000,0xaf643000,0x2a1f8000,0x2f64b000,
0x80008000,0x80000000,0x80000000,0x0,0x80000000,0x80000000,0x80000000,0x80000000,0xb0003000,0xb0003000,0xb0003000,0xb0003000,0xb0003000,0xb0003000,0xb0003000,0xb0003000,
0x3000b000,0x3000b000,0x3000b000,0x3000b000,0x3000b000,0x3000b000,0x3000b000,0x3000b000,0x80000000,0x80000000,0x80008000,0x80008000,0x80000000,0x80008000,0x80008000,0x80008000,
0x2f64ada8,0x2a1fada8,0xaf642da8,0xaa1f2da8,0x2a1f8000,0x2f64b000,0xaa1f8000,0xaf643000,0xaa1f2da8,0x2f64ada8,0x2a1fada8,0xaf642da8,0xaf643000,0x2a1f0000,0x2f64b000,0xaa1f8000,
0x263eac72,0xafd92ea7,0xa63e2c72,0x2fd9aea7,0x2ea7afd9,0xac72263e,0xaea72fd9,0x2c72a63e,0x2fd9aea7,0x263eac72,0xafd92ea7,0xa63e2c72,0x2c72a63e,0x2ea7afd9,0xac72263e,0xaea72fd9,
0xada83000,0x2da8b000,0xada83000,0x2da8b000,0x2da80000,0xada88000,0x2da88000,0xada88000,0x2da88000,0xada88000,0x2da80000,0xada88000,0x2da8b000,0xada83000,0x2da8b000,0xada83000,
0x2f64aa1f,0xaf642a1f,0x2f64aa1f,0xaf642a1f,0x2a1faf64,0xaa1f2f64,0x2a1faf64,0xaa1f2f64,0x2a1faf64,0xaa1f2f64,0x2a1faf64,0xaa1f2f64,0xaf642a1f,0x2f64aa1f,0xaf642a1f,0x2f64aa1f,
0x2f64ada8,0x2a1f2da8,0xaf642da8,0xaa1fada8,0xaa1f3000,0xaf648000,0x2a1fb000,0x2f640000,0xaa1fada8,0x2f64ada8,0x2a1f2da8,0xaf642da8,0x2f648000,0xaa1f3000,0xaf648000,0x2a1fb000,
0xaea7a63e,0x2c72afd9,0x2ea7263e,0xac722fd9,0x2fd9ac72,0x263e2ea7,0xafd92c72,0xa63eaea7,0xac722fd9,0xaea7a63e,0x2c72afd9,0x2ea7263e,0xa63eaea7,0x2fd9ac72,0x263e2ea7,0xafd92c72,
0xada8ada8,0xada8ada8,0xada8ada8,0xada8ada8,0x2da82da8,0x2da82da8,0x2da82da8,0x2da82da8,0x2da8ada8,0x2da8ada8,0x2da8ada8,0x2da8ada8,0xada82da8,0xada82da8,0xada82da8,0xada82da8,
0x30008000,0x30000000,0x30000000,0x30000000,0xb0008000,0xb0008000,0xb0008000,0xb0000000,0x80003000,0x80003000,0x80003000,0x3000,0xb000,0x8000b000,0xb000,0xb000,
0x2ea7a63e,0xac72afd9,0xaea7263e,0x2c722fd9,0xafd9ac72,0xa63e2ea7,0x2fd92c72,0x263eaea7,0x2c722fd9,0x2ea7a63e,0xac72afd9,0xaea7263e,0x263eaea7,0xafd9ac72,0xa63e2ea7,0x2fd92c72,
0xaa1f2da8,0x2f642da8,0x2a1fada8,0xaf64ada8,0x2f648000,0xaa1fb000,0xaf640000,0x2a1f3000,0xaf64ada8,0xaa1f2da8,0x2f642da8,0x2a1fada8,0x2a1f3000,0x2f648000,0xaa1fb000,0xaf648000,
0xaa1faf64,0x2a1f2f64,0xaa1faf64,0x2a1f2f64,0x2f642a1f,0xaf64aa1f,0x2f642a1f,0xaf64aa1f,0xaf64aa1f,0x2f642a1f,0xaf64aa1f,0x2f642a1f,0xaa1faf64,0x2a1f2f64,0xaa1faf64,0x2a1f2f64,
0x2da83000,0xada8b000,0x2da83000,0xada8b000,0xada88000,0x2da88000,0xada88000,0x2da80000,0x2da88000,0xada88000,0x2da80000,0xada80000,0x2da83000,0xada8b000,0x2da83000,0xada8b000,
0xa63eac72,0x2fd92ea7,0x263e2c72,0xafd9aea7,0xaea7afd9,0x2c72263e,0x2ea72fd9,0xac72a63e,0xafd9aea7,0xa63eac72,0x2fd92ea7,0x263e2c72,0xac72a63e,0xaea7afd9,0x2c72263e,0x2ea72fd9,
0x2a1f2da8,0xaf64ada8,0xaa1fada8,0x2f642da8,0x2f643000,0xaa1f8000,0xaf64b000,0x2a1f0000,0x2f642da8,0x2a1f2da8,0xaf64ada8,0xaa1fada8,0x2a1f8000,0x2f643000,0xaa1f8000,0xaf64b000,
0x3c003c00,0x3c003c00,0x3c003c00,0x3c003c00,0x3c003c00,0x3c003c00,0x3c003c00,0x3c003c00,0x80008000,0x80008000,0x80008000,0x80008000,0x80008000,0x80008000,0x80008000,0x80008000,
0x3bd93c00,0x3aa73b64,0x387239a8,0x323e361f,0xb23e0000,0xb872b61f,0xbaa7b9a8,0xbbd9bb64,0xb23e8000,0xb872b61f,0xbaa7b9a8,0xbbd9bb64,0xbbd9bc00,0xbaa7bb64,0xb872b9a8,0xb23eb61f,
0xbb64bc00,0xb61fb9a8,0x361f8000,0x3b6439a8,0x3b643c00,0x361f39a8,0xb61f0000,0xbb64b9a8,0x361f8000,0x3b6439a8,0x3b643c00,0x361f39a8,0xb61f8000,0xbb64b9a8,0xbb64bc00,0xb61fb9a8,
0x38728000,0x3bd93b64,0x323e39a8,0xbaa7b61f,0x3aa73c00,0xb23e361f,0xbbd9b9a8,0xb872bb64,0x3aa73c00,0xb23e361f,0xbbd9b9a8,0xb872bb64,0xb8728000,0xbbd9bb64,0xb23eb9a8,0x3aa7361f,
0xbc008000,0x3c008000,0xbc000000,0x3c008000,0xbc000000,0x3c008000,0xbc000000,0x3c008000,0x3c00,0x8000bc00,0x3c00,0x8000bc00,0x3c00,0x8000bc00,0x80003c00,0x8000bc00,
0xbbd98000,0x3aa7361f,0xb872b9a8,0x323e3b64,0x323ebc00,0xb8723b64,0x3aa7b9a8,0xbbd9361f,0xb23e3c00,0x3872bb64,0xbaa739a8,0x3bd9b61f,0xbbd90000,0x3aa7361f,0xb872b9a8,0x323e3b64,
0x3b648000,0xb61fb9a8,0xb61f3c00,0x3b64b9a8,0xbb648000,0x361f39a8,0x361fbc00,0xbb6439a8,0x361fbc00,0xbb6439a8,0x3b648000,0xb61fb9a8,0xb61f3c00,0x3b64b9a8,0xbb640000,0x361f39a8,
0xb8723c00,0x3bd9b61f,0xb23eb9a8,0xbaa73b64,0xbaa78000,0xb23e3b64,0x3bd9b9a8,0xb872b61f,0x3aa78000,0x323ebb64,0xbbd939a8,0x3872361f,0xb8723c00,0x3bd9b61f,0xb23eb9a8,0xbaa73b64,
0xbbd93c00,0xbaa73b64,0xb87239a8,0xb23e361f,0x323e8000,0x3872b61f,0x3aa7b9a8,0x3bd9bb64,0x323e8000,0x3872b61f,0x3aa7b9a8,0x3bd9bb64,0x3bd9bc00,0x3aa7bb64,0x3872b9a8,0x323eb61f,
0xbc003c00,0xbc003c00,0xbc003c00,0xbc003c00,0xbc003c00,0xbc003c00,0xbc003c00,0xbc003c00,0x80008000,0x80000000,0x80000000,0x80000000,0x80000000,0x80000000,0x0,0x80000000,
0xb8728000,0xbbd93b64,0xb23e39a8,0x3aa7b61f,0xbaa73c00,0x323e361f,0x3bd9b9a8,0x3872bb64,0xbaa73c00,0x323e361f,0x3bd9b9a8,0x3872bb64,0x38728000,0x3bd9bb64,0x323eb9a8,0xbaa7361f,
0x3b64bc00,0x361fb9a8,0xb61f8000,0xbb6439a8,0xbb643c00,0xb61f39a8,0x361f0000,0x3b64b9a8,0xb61f8000,0xbb6439a8,0xbb643c00,0xb61f39a8,0x361f8000,0x3b64b9a8,0x3b64bc00,0x361fb9a8,
0x3bd98000,0xbaa7361f,0x3872b9a8,0xb23e3b64,0xb23ebc00,0x38723b64,0xbaa7b9a8,0x3bd9361f,0x323e3c00,0xb872bb64,0x3aa739a8,0xbbd9b61f,0x3bd98000,0xbaa7361f,0x3872b9a8,0xb23e3b64,
0x3c008000,0xbc008000,0x3c000000,0xbc008000,0x3c000000,0xbc008000,0x3c000000,0xbc000000,0x80003c00,0xbc00,0x80003c00,0x8000bc00,0x80003c00,0xbc00,0x80003c00,0xbc00,
0x38723c00,0xbbd9b61f,0x323eb9a8,0x3aa73b64,0x3aa78000,0x323e3b64,0xbbd9b9a8,0x3872b61f,0xbaa78000,0xb23ebb64,0x3bd939a8,0xb872361f,0x38723c00,0xbbd9b61f,0x323eb9a8,0x3aa73b64,
0xbb640000,0x361fb9a8,0x361f3c00,0xbb64b9a8,0x3b648000,0xb61f39a8,0xb61fbc00,0x3b6439a8,0xb61fbc00,0x3b6439a8,0xbb640000,0x361fb9a8,0x361f3c00,0xbb64b9a8,0x3b648000,0xb61f39a8,
0x39a83c00,0xb9a80000,0xb9a8bc00,0x39a88000,0x39a83c00,0xb9a80000,0xb9a8bc00,0x39a88000,0xb9a88000,0xb9a8bc00,0x39a88000,0x39a83c00,0xb9a80000,0xb9a8bc00,0x39a88000,0x39a83c00,
0x38723c00,0xbbd9b61f,0x323eb9a8,0x3aa73b64,0xbaa70000,0xb23ebb64,0x3bd939a8,0xb872361f,0xbaa78000,0xb23ebb64,0x3bd939a8,0xb872361f,0xb872bc00,0x3bd9361f,0xb23e39a8,0xbaa7bb64,
0xb61fbc00,0x3b6439a8,0xbb640000,0x361fb9a8,0x361f3c00,0xbb64b9a8,0x3b648000,0xb61f39a8,0x3b648000,0xb61f39a8,0xb61fbc00,0x3b6439a8,0xbb648000,0x361fb9a8,0x361f3c00,0xbb64b9a8,
0x3bd98000,0xbaa7361f,0x3872b9a8,0xb23e3b64,0x323e3c00,0xb872bb64,0x3aa739a8,0xbbd9b61f,0x323e3c00,0xb872bb64,0x3aa739a8,0xbbd9b61f,0xbbd98000,0x3aa7b61f,0xb87239a8,0x323ebb64,
0xb9a88000,0xb9a83c00,0x39a88000,0x39a8bc00,0xb9a80000,0xb9a83c00,0x39a88000,0x39a8bc00,0xb9a83c00,0x39a88000,0x39a8bc00,0xb9a80000,0xb9a83c00,0x39a88000,0x39a8bc00,0xb9a88000,
0xb8728000,0xbbd93b64,0xb23e39a8,0x3aa7b61f,0x3aa7bc00,0xb23eb61f,0xbbd939a8,0xb8723b64,0xbaa73c00,0x323e361f,0x3bd9b9a8,0x3872bb64,0xb8728000,0xbbd93b64,0xb23e39a8,0x3aa7b61f,
0x361f8000,0x3b64b9a8,0x3b64bc00,0x361fb9a8,0xb61f8000,0xbb6439a8,0xbb643c00,0xb61f39a8,0x3b64bc00,0x361fb9a8,0xb61f8000,0xbb6439a8,0xbb643c00,0xb61f39a8,0x361f8000,0x3b64b9a8,
0xbbd93c00,0xbaa73b64,0xb87239a8,0xb23e361f,0xb23e8000,0xb872361f,0xbaa739a8,0xbbd93b64,0x323e8000,0x3872b61f,0x3aa7b9a8,0x3bd9bb64,0xbbd93c00,0xbaa73b64,0xb87239a8,0xb23e361f,
0xb8723c00,0x3bd9b61f,0xb23eb9a8,0xbaa73b64,0x3aa78000,0x323ebb64,0xbbd939a8,0x3872361f,0x3aa78000,0x323ebb64,0xbbd939a8,0x3872361f,0x3872bc00,0xbbd9361f,0x323e39a8,0x3aa7bb64,
0xb9a83c00,0x39a80000,0x39a8bc00,0xb9a88000,0xb9a83c00,0x39a88000,0x39a8bc00,0xb9a88000,0x39a88000,0x39a8bc00,0xb9a88000,0xb9a83c00,0x39a80000,0x39a8bc00,0xb9a88000,0xb9a83c00,
0xbbd98000,0x3aa7361f,0xb872b9a8,0x323e3b64,0xb23e3c00,0x3872bb64,0xbaa739a8,0x3bd9b61f,0xb23e3c00,0x3872bb64,0xbaa739a8,0x3bd9b61f,0x3bd98000,0xbaa7b61f,0x387239a8,0xb23ebb64,
0x361fbc00,0xbb6439a8,0x3b640000,0xb61fb9a8,0xb61f3c00,0x3b64b9a8,0xbb648000,0x361f39a8,0xbb648000,0x361f39a8,0x361fbc00,0xbb6439a8,0x3b648000,0xb61fb9a8,0xb61f3c00,0x3b64b9a8,
0x38728000,0x3bd93b64,0x323e39a8,0xbaa7b61f,0xbaa7bc00,0x323eb61f,0x3bd939a8,0x38723b64,0x3aa73c00,0xb23e361f,0xbbd9b9a8,0xb872bb64,0x38728000,0x3bd93b64,0x323e39a8,0xbaa7b61f,
0x39a88000,0x39a83c00,0xb9a88000,0xb9a8bc00,0x39a80000,0x39a83c00,0xb9a80000,0xb9a8bc00,0x39a83c00,0xb9a88000,0xb9a8bc00,0x39a88000,0x39a83c00,0xb9a88000,0xb9a8bc00,0x39a80000,
0x3bd93c00,0x3aa73b64,0x387239a8,0x323e361f,0x323e8000,0x3872361f,0x3aa739a8,0x3bd93b64,0xb23e8000,0xb872b61f,0xbaa7b9a8,0xbbd9bb64,0x3bd93c00,0x3aa73b64,0x387239a8,0x323e361f,
0xb61f8000,0xbb64b9a8,0xbb64bc00,0xb61fb9a8,0x361f8000,0x3b6439a8,0x3b643c00,0x361f39a8,0xbb64bc00,0xb61fb9a8,0x361f0000,0x3b6439a8,0x3b643c00,0x361f39a8,0xb61f8000,0xbb64b9a8,
0x0,0x0,0x0,0x0,0x0,0x0,0x0,0x0,0x3c003c00,0x3c003c00,0x3c003c00,0x3c003c00,0x3c003c00,0x3c003c00,0x3c003c00,0x3c003c00,
0x323e0000,0x3872361f,0x3aa739a8,0x3bd93b64,0x3bd93c00,0x3aa73b64,0x387239a8,0x323e361f,0x3bd93c00,0x3aa73b64,0x387239a8,0x323e361f,0xb23e0000,0xb872b61f,0xbaa7b9a8,0xbbd9bb64,
0xb61f0000,0xbb64b9a8,0xbb64bc00,0xb61fb9a8,0x361f0000,0x3b6439a8,0x3b643c00,0x361f39a8,0xbb64bc00,0xb61fb9a8,0x361f8000,0x3b6439a8,0x3b643c00,0x361f39a8,0xb61f0000,0xbb64b9a8,
0xbaa7bc00,0x323eb61f,0x3bd939a8,0x38723b64,0x38720000,0x3bd93b64,0x323e39a8,0xbaa7b61f,0x38728000,0x3bd93b64,0x323e39a8,0xbaa7b61f,0x3aa73c00,0xb23e361f,0xbbd9b9a8,0xb872bb64,
0x3c00,0x8000bc00,0x3c00,0x8000bc00,0x3c00,0x8000bc00,0x80003c00,0x8000bc00,0x3c000000,0xbc000000,0x3c008000,0xbc000000,0x3c008000,0xbc000000,0x3c008000,0xbc000000,
0xb23e3c00,0x3872bb64,0xbaa739a8,0x3bd9b61f,0xbbd90000,0x3aa7361f,0xb872b9a8,0x323e3b64,0x3bd90000,0xbaa7b61f,0x387239a8,0xb23ebb64,0xb23e3c00,0x3872bb64,0xbaa739a8,0x3bd9b61f,
0x361fbc00,0xbb6439a8,0x3b648000,0xb61fb9a8,0xb61f3c00,0x3b64b9a8,0xbb640000,0x361f39a8,0xbb640000,0x361f39a8,0x361fbc00,0xbb6439a8,0x3b640000,0xb61fb9a8,0xb61f3c00,0x3b64b9a8,
0x3aa78000,0x323ebb64,0xbbd939a8,0x3872361f,0xb8723c00,0x3bd9b61f,0xb23eb9a8,0xbaa73b64,0x3872bc00,0xbbd9361f,0x323e39a8,0x3aa7bb64,0x3aa70000,0x323ebb64,0xbbd939a8,0x3872361f,
0xb23e0000,0xb872361f,0xbaa739a8,0xbbd93b64,0xbbd93c00,0xbaa73b64,0xb87239a8,0xb23e361f,0xbbd93c00,0xbaa73b64,0xb87239a8,0xb23e361f,0x323e8000,0x3872b61f,0x3aa7b9a8,0x3bd9bb64,
0x0,0x8000,0x8000,0x8000,0x8000,0x8000,0x80008000,0x8000,0xbc003c00,0xbc003c00,0xbc003c00,0xbc003c00,0xbc003c00,0xbc003c00,0xbc003c00,0xbc003c00,
0x3aa7bc00,0xb23eb61f,0xbbd939a8,0xb8723b64,0xb8720000,0xbbd93b64,0xb23e39a8,0x3aa7b61f,0xb8728000,0xbbd93b64,0xb23e39a8,0x3aa7b61f,0xbaa73c00,0x323e361f,0x3bd9b9a8,0x3872bb64,
0x361f0000,0x3b64b9a8,0x3b64bc00,0x361fb9a8,0xb61f0000,0xbb6439a8,0xbb643c00,0xb61f39a8,0x3b64bc00,0x361fb9a8,0xb61f8000,0xbb6439a8,0xbb643c00,0xb61f39a8,0x361f0000,0x3b64b9a8,
0x323e3c00,0xb872bb64,0x3aa739a8,0xbbd9b61f,0x3bd98000,0xbaa7361f,0x3872b9a8,0xb23e3b64,0xbbd90000,0x3aa7b61f,0xb87239a8,0x323ebb64,0x323e3c00,0xb872bb64,0x3aa739a8,0xbbd9b61f,
0x80003c00,0xbc00,0x80003c00,0x8000bc00,0x80003c00,0xbc00,0x80003c00,0xbc00,0xbc000000,0x3c000000,0xbc008000,0x3c000000,0xbc008000,0x3c000000,0xbc008000,0x3c008000,
0xbaa78000,0xb23ebb64,0x3bd939a8,0xb872361f,0x38723c00,0xbbd9b61f,0x323eb9a8,0x3aa73b64,0xb872bc00,0x3bd9361f,0xb23e39a8,0xbaa7bb64,0xbaa70000,0xb23ebb64,0x3bd939a8,0xb872361f,
0xb61fbc00,0x3b6439a8,0xbb640000,0x361fb9a8,0x361f3c00,0xbb64b9a8,0x3b648000,0xb61f39a8,0x3b648000,0xb61f39a8,0xb61fbc00,0x3b6439a8,0xbb640000,0x361fb9a8,0x361f3c00,0xbb64b9a8,
0x39a80000,0x39a83c00,0xb9a80000,0xb9a8bc00,0x39a88000,0x39a83c00,0xb9a80000,0xb9a8bc00,0x39a83c00,0xb9a80000,0xb9a8bc00,0x39a88000,0x39a83c00,0xb9a80000,0xb9a8bc00,0x39a88000,
0x3aa70000,0x323e3b64,0xbbd9b9a8,0x3872b61f,0x38723c00,0xbbd9b61f,0x323eb9a8,0x3aa73b64,0x38723c00,0xbbd9b61f,0x323eb9a8,0x3aa73b64,0xbaa70000,0xb23ebb64,0x3bd939a8,0xb872361f,
0xbb640000,0x361fb9a8,0x361f3c00,0xbb64b9a8,0x3b640000,0xb61f39a8,0xb61fbc00,0x3b6439a8,0xb61fbc00,0x3b6439a8,0xbb640000,0x361fb9a8,0x361f3c00,0xbb64b9a8,0x3b648000,0xb61f39a8,
0xb23ebc00,0x38723b64,0xbaa7b9a8,0x3bd9361f,0x3bd90000,0xbaa7361f,0x3872b9a8,0xb23e3b64,0x3bd98000,0xbaa7361f,0x3872b9a8,0xb23e3b64,0x323e3c00,0xb872bb64,0x3aa739a8,0xbbd9b61f,
0xb9a83c00,0x39a88000,0x39a8bc00,0xb9a80000,0xb9a83c00,0x39a88000,0x39a8bc00,0xb9a88000,0x39a80000,0x39a8bc00,0xb9a80000,0xb9a83c00,0x39a88000,0x39a8bc00,0xb9a80000,0xb9a83c00,
0xbaa73c00,0x323e361f,0x3bd9b9a8,0x3872bb64,0xb8728000,0xbbd93b64,0xb23e39a8,0x3aa7b61f,0x38720000,0x3bd9bb64,0x323eb9a8,0xbaa7361f,0xbaa73c00,0x323e361f,0x3bd9b9a8,0x3872bb64,
0x3b64bc00,0x361fb9a8,0xb61f8000,0xbb6439a8,0xbb643c00,0xb61f39a8,0x361f8000,0x3b64b9a8,0xb61f0000,0xbb6439a8,0xbb643c00,0xb61f39a8,0x361f0000,0x3b64b9a8,0x3b64bc00,0x361fb9a8,
0x323e8000,0x3872b61f,0x3aa7b9a8,0x3bd9bb64,0xbbd93c00,0xbaa73b64,0xb87239a8,0xb23e361f,0x3bd9bc00,0x3aa7bb64,0x3872b9a8,0x323eb61f,0x323e0000,0x3872b61f,0x3aa7b9a8,0x3bd9bb64,
0xbaa70000,0xb23e3b64,0x3bd9b9a8,0xb872b61f,0xb8723c00,0x3bd9b61f,0xb23eb9a8,0xbaa73b64,0xb8723c00,0x3bd9b61f,0xb23eb9a8,0xbaa73b64,0x3aa78000,0x323ebb64,0xbbd939a8,0x3872361f,
0xb9a80000,0xb9a83c00,0x39a80000,0x39a8bc00,0xb9a88000,0xb9a83c00,0x39a80000,0x39a8bc00,0xb9a83c00,0x39a80000,0x39a8bc00,0xb9a88000,0xb9a83c00,0x39a88000,0x39a8bc00,0xb9a88000,
0x323ebc00,0xb8723b64,0x3aa7b9a8,0xbbd9361f,0xbbd90000,0x3aa7361f,0xb872b9a8,0x323e3b64,0xbbd98000,0x3aa7361f,0xb872b9a8,0x323e3b64,0xb23e3c00,0x3872bb64,0xbaa739a8,0x3bd9b61f,
0x3b640000,0xb61fb9a8,0xb61f3c00,0x3b64b9a8,0xbb640000,0x361f39a8,0x361fbc00,0xbb6439a8,0x361fbc00,0xbb6439a8,0x3b640000,0xb61fb9a8,0xb61f3c00,0x3b64b9a8,0xbb648000,0x361f39a8,
0x3aa73c00,0xb23e361f,0xbbd9b9a8,0xb872bb64,0x38728000,0x3bd93b64,0x323e39a8,0xbaa7b61f,0xb8720000,0xbbd9bb64,0xb23eb9a8,0x3aa7361f,0x3aa73c00,0xb23e361f,0xbbd9b9a8,0xb872bb64,
0x39a83c00,0xb9a88000,0xb9a8bc00,0x39a88000,0x39a83c00,0xb9a88000,0xb9a8bc00,0x39a80000,0xb9a80000,0xb9a8bc00,0x39a80000,0x39a83c00,0xb9a88000,0xb9a8bc00,0x39a88000,0x39a83c00,
0xb23e8000,0xb872b61f,0xbaa7b9a8,0xbbd9bb64,0x3bd93c00,0x3aa73b64,0x387239a8,0x323e361f,0xbbd9bc00,0xbaa7bb64,0xb872b9a8,0xb23eb61f,0xb23e0000,0xb872b61f,0xbaa7b9a8,0xbbd9bb64,
0xbb64bc00,0xb61fb9a8,0x361f0000,0x3b6439a8,0x3b643c00,0x361f39a8,0xb61f8000,0xbb64b9a8,0x361f0000,0x3b6439a8,0x3b643c00,0x361f39a8,0xb61f0000,0xbb64b9a8,0xbb64bc00,0xb61fb9a8,
};
__device__ __align__(1024) bf16 g_x1T[DM * XP];
__device__ __align__(1024) bf16 g_x2T[DM * XP];
__device__ __align__(1024) unsigned g_xcnt[10][4][32];
__device__ __align__(1024) uint4 g_of[8][16][1280];
__device__ __align__(1024) float g_fs[2][SEQ];

#define TS_SMEM 0
#define TS_DECL
#define TS_ARG
#define TS_PASS
#define TS_PHASE(p)
#define TS(i)
#define TSX(row, i)
#define TS_BEGIN
#define TS_END

struct cplx { float r, i; };
__device__ __forceinline__ cplx cmul(cplx a, cplx b) {
    cplx o;
    o.r = fmaf(a.r, b.r, -a.i * b.i);
    o.i = fmaf(a.r, b.i, a.i * b.r);
    return o;
}
__device__ __forceinline__ cplx csq(cplx a) {
    cplx o;
    o.r = fmaf(a.r, a.r, -a.i * a.i);
    o.i = 2.f * a.r * a.i;
    return o;
}
__device__ __forceinline__ cplx cexp_p(float arl, float ai, float p) {
    float mag = ex2(arl * p);
    float ang = ai * p;
    float n = rintf(ang * 0.15915494309189535f);
    float r = fmaf(n, -6.2831854820251465f, ang);
    r = fmaf(n, 1.7484555e-7f, r);
    cplx o;
    o.r = mag * __cosf(r);
    o.i = mag * __sinf(r);
    return o;
}

__device__ __forceinline__ uint32_t pack2h(float lo, float hi) {
    uint32_t r;
    asm("cvt.rn.f16x2.f32 %0, %1, %2;" : "=r"(r) : "f"(hi), "f"(lo));
    return r;
}
__device__ __forceinline__ uint32_t hmul(uint32_t a, uint32_t b) { uint32_t d; asm("mul.rn.f16x2 %0, %1, %2;" : "=r"(d) : "r"(a), "r"(b)); return d; }
__device__ __forceinline__ uint32_t hfma(uint32_t a, uint32_t b, uint32_t c) { uint32_t d; asm("fma.rn.f16x2 %0, %1, %2, %3;" : "=r"(d) : "r"(a), "r"(b), "r"(c)); return d; }
__device__ __forceinline__ uint32_t hfms(uint32_t a, uint32_t b, uint32_t c) {
    uint32_t d;
    asm("{\n.reg .b32 n;\nneg.f16x2 n, %1;\nfma.rn.f16x2 %0, n, %2, %3;\n}" : "=r"(d) : "r"(a), "r"(b), "r"(c));
    return d;
}
__device__ __forceinline__ uint32_t hadd(uint32_t a, uint32_t b) { uint32_t d; asm("add.rn.f16x2 %0, %1, %2;" : "=r"(d) : "r"(a), "r"(b)); return d; }
__device__ __forceinline__ uint32_t hsub(uint32_t a, uint32_t b) { uint32_t d; asm("sub.rn.f16x2 %0, %1, %2;" : "=r"(d) : "r"(a), "r"(b)); return d; }
__device__ __forceinline__ uint4 ldg_tab(int tab, int t) { return ldg128((const uint4*)c_fft + t + tab * 128); }
__device__ __forceinline__ uint32_t u4(const uint4& v, int i) { return i == 0 ? v.x : i == 1 ? v.y : i == 2 ? v.z : v.w; }
struct cpair { uint32_t r, i; };
__device__ __forceinline__ cpair pmul(cpair p, uint32_t z) {
    const __half2 zv = *reinterpret_cast<const __half2*>(&z), pr = *reinterpret_cast<const __half2*>(&p.r), pi = *reinterpret_cast<const __half2*>(&p.i);
    const __half2 zr = __low2half2(zv), zi = __high2half2(zv);
    const __half2 a = __hfma2(__hneg2(pi), zi, __hmul2(pr, zr)), b = __hfma2(pi, zr, __hmul2(pr, zi));
    return {*reinterpret_cast<const uint32_t*>(&a), *reinterpret_cast<const uint32_t*>(&b)};
}
__device__ __forceinline__ uint32_t packz(cplx z) { return pack2h(z.r, z.i); }
__device__ __forceinline__ void wgmma_kg(float (&d)[24], uint64_t da, uint64_t db, int scale_d) {
    asm volatile("{\n.reg .pred p;\nsetp.ne.b32 p, %26, 0;\n"
                 "wgmma.mma_async.sync.aligned.m64n48k16.f32.f16.f16 "
                 "{%0,%1,%2,%3,%4,%5,%6,%7,%8,%9,%10,%11,%12,%13,%14,%15,%16,%17,%18,%19,%20,%21,%22,%23}, %24, %25, p, 1, 1, 1, 1;\n}\n"
                 : "+f"(d[0]), "+f"(d[1]), "+f"(d[2]), "+f"(d[3]), "+f"(d[4]), "+f"(d[5]), "+f"(d[6]), "+f"(d[7]), "+f"(d[8]), "+f"(d[9]),
                   "+f"(d[10]), "+f"(d[11]), "+f"(d[12]), "+f"(d[13]), "+f"(d[14]), "+f"(d[15]), "+f"(d[16]), "+f"(d[17]), "+f"(d[18]), "+f"(d[19]),
                   "+f"(d[20]), "+f"(d[21]), "+f"(d[22]), "+f"(d[23])
                 : "l"(da), "l"(db), "r"(scale_d));
}

struct SsmParams { const bf16 *lar, *aim, *cre, *cim, *logdt, *dskip; const unsigned* epoch; };
constexpr int KG_TABLES = 6 * 16384, KG_RES = 1664;
struct KgShared { uint32_t kmax[6], kexp[6]; float cinv[6], tap0[6]; };
#define KS(f, i) (ks + (uint32_t)offsetof(KgShared, f) + 4 * (i))
struct KgParams { uint32_t l[3], a[3], r[3], i[3], dt, ds; };

__device__ __forceinline__ int cta_channel(int bx, int i) { return i < 2 ? 2 * bx + i : i < 4 ? 382 + 2 * bx + i : 256 + bx; }
__device__ __forceinline__ bool kg_is_hi(int warp) { return ((warp >> 1) ^ (warp >> 2)) & 1; }
__device__ __forceinline__ void kgen_load(KgParams& kp, int bx, int warp, int lane, const SsmParams& sp) {
    const int d = cta_channel(bx, 2 * (warp >> 2) + (warp & 1)), idx = d * (NMODE / 2) + lane;
    const bf16 *pr = kg_is_hi(warp) ? sp.cre : sp.lar, *pi = kg_is_hi(warp) ? sp.cim : sp.aim;
    kp.dt = __ldg((const uint16_t*)sp.logdt + d);
#pragma unroll
    for (int j = 0; j < 3; j++) {
        kp.l[j] = __ldg((const uint32_t*)sp.lar + idx + 32 * j); kp.a[j] = __ldg((const uint32_t*)sp.aim + idx + 32 * j);
        kp.r[j] = __ldg((const uint32_t*)pr + idx + 32 * j); kp.i[j] = __ldg((const uint32_t*)pi + idx + 32 * j);
    }
    kp.ds = __ldg((const uint16_t*)sp.dskip + cta_channel(bx, warp >> 1));
}

struct KgAnchors { uint32_t v[8]; };
__device__ __forceinline__ KgAnchors kg_anchor_lo(const KgParams& kp, uint32_t sel, float dt) {
    auto B = [&](uint32_t v) { return __uint_as_float(__byte_perm(v, 0u, sel)); };
    const float arl = -rbf(ex2(B(kp.l[0]) * 1.4426950408889634f)) * dt * 1.4426950408889634f, ai = B(kp.a[0]) * dt;
    const cplx z8 = cexp_p(arl, ai, 8.f), z16 = csq(z8), z24 = cmul(z16, z8), z32 = csq(z16), z64 = csq(z32), z128 = csq(z64), z192 = cmul(z128, z64);
    return {{pack2h(1.f, z8.r), pack2h(0.f, z8.i), pack2h(z16.r, z24.r), pack2h(z16.i, z24.i), packz(z32), packz(z64), packz(z128), packz(z192)}};
}
__device__ __forceinline__ KgAnchors kg_anchor_hi(const KgParams& kp, uint32_t sel, float dt, float cs) {
    auto B = [&](uint32_t v) { return __uint_as_float(__byte_perm(v, 0u, sel)); };
    const float arl = -rbf(ex2(B(kp.l[0]) * 1.4426950408889634f)) * dt * 1.4426950408889634f, ai = B(kp.a[0]) * dt;
    const cplx z1 = cexp_p(arl, -ai, 1.f), z2 = csq(z1), z4 = csq(z2), z256 = cexp_p(arl, -ai, 256.f), z512 = csq(z256), z1024 = csq(z512);
    const cplx H0 = {B(kp.r[0]) * cs, -B(kp.i[0]) * cs}, H4 = cmul(H0, z4);
    return {{pack2h(H0.r, H4.r), pack2h(H0.i, H4.i), packz(z1), packz(z2), packz(z256), packz(z512), packz(z1024), 0u}};
}

template <class Idle>
__device__ __forceinline__ void kgen_tables(KgParams& kp, uint32_t scr, uint32_t dump, uint32_t ks, int warp, int lane, Idle idle TS_ARG) {
    const int wg = warp >> 2, half = warp & 1, sw = lane & 7;
    const bool hi = kg_is_hi(warp);
    TS(23);
    const float dt = rbf(ex2(bf_lo(kp.dt) * 1.4426950408889634f));
    uint32_t sel = (wg == 2 && half) ? 0x3244u : 0x1044u;
    float cs = 0.f;
    KgAnchors an;
    if (hi) {
        uint32_t m = 0;
#pragma unroll
        for (int j = 0; j < 3; j++) m = __vmaxu2(m, __vmaxu2(kp.r[j] & 0x7FFF7FFFu, kp.i[j] & 0x7FFF7FFFu));
        m = __reduce_max_sync(~0u, max(m << 16, m & 0xFFFF0000u));
        const uint32_t e = min(max(__float_as_uint(2.f * dt * __uint_as_float(m)) >> 23, 2u), 252u);
        cs = 2.f * dt * __uint_as_float((253u - e) << 23);
        if (lane == 0) { sts32(KS(cinv, 2 * wg + half), (e + 1u) << 23); sts32(KS(kmax, 2 * wg + half), 0u); }
        an = kg_anchor_hi(kp, sel, dt, cs);
    } else {
        an = kg_anchor_lo(kp, sel, dt);
    }
    float acc[24];
#pragma unroll
    for (int i = 0; i < 24; i++) acc[i] = 0.f;
    uint32_t tb = scr + 2 * wg * 16384 + lane * 128;
    uint64_t da = mkdesc(scr + 2 * wg * 16384, 4096, 1024, 1);
    int flip = 16384;
#pragma unroll 1
    for (int c = wg == 2 ? 1 : 0, step = wg == 2 ? 2 : 1; c < 6; c += step) {
        if (wg < 2) sel ^= 0x2200u;
        if (!hi) {
            if (c & 1) { kp.l[0] = kp.l[1]; kp.l[1] = kp.l[2]; kp.a[0] = kp.a[1]; kp.a[1] = kp.a[2]; }
            cpair p[4];
            p[0] = {an.v[0], an.v[1]}; p[1] = {an.v[2], an.v[3]};
            p[2] = pmul(p[0], an.v[4]); p[3] = pmul(p[1], an.v[4]);
#pragma unroll
            for (int j = 0; j < 4; j++) {
                cpair v[4];
#pragma unroll
                for (int i = 0; i < 4; i++) v[i] = j ? pmul(p[i], an.v[4 + j]) : p[i];
                const uint32_t a = tb + (((4 * half + j) ^ sw) << 4);
                sts128(a, make_uint4(v[0].r, v[1].r, v[2].r, v[3].r));
                sts128(a + 4096, make_uint4(v[0].i, v[1].i, v[2].i, v[3].i));
            }
            an = kg_anchor_lo(kp, sel, dt);
        } else {
            if (c & 1) {
#pragma unroll
                for (int j = 0; j < 2; j++) { kp.l[j] = kp.l[j + 1]; kp.a[j] = kp.a[j + 1]; kp.r[j] = kp.r[j + 1]; kp.i[j] = kp.i[j + 1]; }
            }
            const uint32_t h1 = an.v[2], h2 = an.v[3], h256 = an.v[4], h512 = an.v[5], h1024 = an.v[6];
            cpair p[11];
            p[0] = {an.v[0], an.v[1]};
            p[1] = pmul(p[0], h2); p[2] = pmul(p[0], h1); p[3] = pmul(p[1], h1);
            p[4] = pmul(p[0], h256); p[5] = pmul(p[1], h256); p[6] = pmul(p[0], h512); p[7] = pmul(p[4], h512);
            p[8] = pmul({__byte_perm(p[0].r, p[4].r, 0x5410), __byte_perm(p[0].i, p[4].i, 0x5410)}, h1024);
            p[9] = pmul(p[8], h512); p[10] = pmul(p[8], h1024);
#pragma unroll
            for (int j = 0; j < 3; j++) {
                const uint32_t a = tb + 8192 + (((3 * half + j) ^ sw) << 4);
                sts128(a, make_uint4(p[4 * j].r, p[4 * j + 1].r, p[4 * j + 2].r, p[j < 2 ? 4 * j + 3 : 10].r));
                sts128(a + 4096, make_uint4(p[4 * j].i, p[4 * j + 1].i, p[4 * j + 2].i, p[j < 2 ? 4 * j + 3 : 10].i));
            }
            an = kg_anchor_hi(kp, sel, dt, cs);
        }
        if (c == 0) TS(24);
        if (c == 3) TS(25);
        fence_async_smem();
        wg_wait<0>();
        named_bar(5 + wg, 128);
        wg_fence();
#pragma unroll
        for (int k = 0; k < 4; k++) wgmma_kg(acc, da + k * 128, da + 512 + k * 128, 1);
        wg_commit();
        tb += flip; da += flip >> 4; flip = -flip;
    }
    const bool up = warp & 2;
    const int r = 2 * wg + up, lo0 = 16 * half + (lane >> 2);
    const uint32_t o = dump + r * KG_RES + lo0 * 52 + 4 * (lane & 3);
    const float ci = __uint_as_float(lds32(KS(cinv, r)));
    const float ds = warp <= 8 ? bf_lo(kp.ds) : 0.f;
    TS(26);
    idle();
    wg_wait<0>();
    float v[12], m = 0.f;
#pragma unroll
    for (int j = 0; j < 12; j++) { v[j] = up ? acc[12 + j] : acc[j]; m = fmaxf(m, fabsf(v[j])); }
#pragma unroll
    for (int j = 0; j < 6; j++) sts32(o + (j & 1) * 416 + (j >> 1) * 16, pack2h(v[2 * j], v[2 * j + 1]));
    const uint32_t mm = __reduce_max_sync(~0u, __float_as_uint(m));
    if (lane == 0) {
        asm volatile("red.shared.max.u32 [%0], %1;" ::"r"(KS(kmax, r)), "r"(mm) : "memory");
        if (!half) sts32(KS(tap0, r), __float_as_uint(fmaf(ci, v[0], ds)));
    }
}
#define F_STAG 4
__device__ __forceinline__ void wgmma_h64_rs(uint32_t (&d)[16], const uint4& a, uint64_t db, int scale_d) {
    asm volatile("{\n.reg .pred p;\nsetp.ne.b32 p, %21, 0;\n"
                 "wgmma.mma_async.sync.aligned.m64n64k16.f16.f16.f16 {%0,%1,%2,%3,%4,%5,%6,%7,%8,%9,%10,%11,%12,%13,%14,%15}, {%16,%17,%18,%19}, %20, p, 1, 1, 1;\n}\n"
                 : "+r"(d[0]), "+r"(d[1]), "+r"(d[2]), "+r"(d[3]), "+r"(d[4]), "+r"(d[5]), "+r"(d[6]), "+r"(d[7]), "+r"(d[8]), "+r"(d[9]),
                   "+r"(d[10]), "+r"(d[11]), "+r"(d[12]), "+r"(d[13]), "+r"(d[14]), "+r"(d[15])
                 : "r"(a.x), "r"(a.y), "r"(a.z), "r"(a.w), "l"(db), "r"(scale_d));
}
template <int TB>
__device__ __forceinline__ void wgmma_h32_rs(uint32_t (&d)[8], const uint4& a, uint64_t db, int scale_d) {
    asm volatile("{\n.reg .pred p;\nsetp.ne.b32 p, %13, 0;\n"
                 "wgmma.mma_async.sync.aligned.m64n32k16.f16.f16.f16 {%0,%1,%2,%3,%4,%5,%6,%7}, {%8,%9,%10,%11}, %12, p, 1, 1, %14;\n}\n"
                 : "+r"(d[0]), "+r"(d[1]), "+r"(d[2]), "+r"(d[3]), "+r"(d[4]), "+r"(d[5]), "+r"(d[6]), "+r"(d[7])
                 : "r"(a.x), "r"(a.y), "r"(a.z), "r"(a.w), "l"(db), "r"(scale_d), "n"(TB));
}
__device__ __forceinline__ void wgmma_s1(uint32_t (&d)[16], const uint4& a, uint64_t db, int scale_d) { wgmma_h64_rs(d, a, db, scale_d); }
__device__ __forceinline__ void wgmma_s1(uint32_t (&d)[8], const uint4& a, uint64_t db, int scale_d) { wgmma_h32_rs<1>(d, a, db, scale_d); }
__device__ __forceinline__ void wgmma_s4(float (&d)[32], const uint4& a, uint64_t db, uint32_t meta, int scale_d) {
    asm volatile("{\n.reg .pred p;\nsetp.ne.b32 p, %38, 0;\n"
                 "wgmma.mma_async.sp.sync.aligned.m64n64k32.f32.f16.f16 {%0,%1,%2,%3,%4,%5,%6,%7,%8,%9,%10,%11,%12,%13,%14,%15,%16,%17,%18,%19,%20,%21,%22,%23,%24,%25,%26,%27,%28,%29,%30,%31}, {%32,%33,%34,%35}, %36, %37, 0, p, 1, 1, 1;\n}\n"
                 : "+f"(d[0]), "+f"(d[1]), "+f"(d[2]), "+f"(d[3]), "+f"(d[4]), "+f"(d[5]), "+f"(d[6]), "+f"(d[7]), "+f"(d[8]), "+f"(d[9]), "+f"(d[10]), "+f"(d[11]), "+f"(d[12]), "+f"(d[13]), "+f"(d[14]), "+f"(d[15]), "+f"(d[16]), "+f"(d[17]), "+f"(d[18]), "+f"(d[19]), "+f"(d[20]), "+f"(d[21]), "+f"(d[22]), "+f"(d[23]), "+f"(d[24]), "+f"(d[25]), "+f"(d[26]), "+f"(d[27]), "+f"(d[28]), "+f"(d[29]), "+f"(d[30]), "+f"(d[31])
                 : "r"(a.x), "r"(a.y), "r"(a.z), "r"(a.w), "l"(db), "r"(meta), "r"(scale_d));
}
__device__ __forceinline__ void wgmma_s4(float (&d)[16], const uint4& a, uint64_t db, uint32_t meta, int scale_d) {
    asm volatile("{\n.reg .pred p;\nsetp.ne.b32 p, %22, 0;\n"
                 "wgmma.mma_async.sp.sync.aligned.m64n32k32.f32.f16.f16 {%0,%1,%2,%3,%4,%5,%6,%7,%8,%9,%10,%11,%12,%13,%14,%15}, {%16,%17,%18,%19}, %20, %21, 0, p, 1, 1, 1;\n}\n"
                 : "+f"(d[0]), "+f"(d[1]), "+f"(d[2]), "+f"(d[3]), "+f"(d[4]), "+f"(d[5]), "+f"(d[6]), "+f"(d[7]), "+f"(d[8]), "+f"(d[9]), "+f"(d[10]), "+f"(d[11]), "+f"(d[12]), "+f"(d[13]), "+f"(d[14]), "+f"(d[15])
                 : "r"(a.x), "r"(a.y), "r"(a.z), "r"(a.w), "l"(db), "r"(meta), "r"(scale_d));
}

__device__ __forceinline__ uint32_t& u4r(uint4& v, int i) { return i == 0 ? v.x : i == 1 ? v.y : i == 2 ? v.z : v.w; }

template <int NC>
__device__ __forceinline__ void fft_stage(const uint32_t (&u)[2][4], int c, uint32_t eo, int w, int lane) {
    const int mi = lane >> 3, mj = lane & 7;
    const uint32_t a = eo + (8 * w + mj) * 128 + (((4 * c + mi) ^ mj) << 4);
    stsm_x4(a, hadd(u[0][0], u[1][0]), hadd(u[0][1], u[1][1]), hadd(u[0][2], u[1][2]), hadd(u[0][3], u[1][3]));
    stsm_x4(NC == 2 ? a + 4096 : a ^ 64, hsub(u[0][0], u[1][0]), hsub(u[0][1], u[1][1]), hsub(u[0][2], u[1][2]), hsub(u[0][3], u[1][3]));
}
template <int NC>
__device__ __forceinline__ void kernel_stage(const uint4 (&ko)[2], uint32_t kt, uint32_t ks, int r, uint32_t eo, int w, int lane) {
    uint32_t u[2][2][4], sc[NC], t0[NC];
#pragma unroll
    for (int c = 0; c < NC; c++) {
        auto L = [](uint32_t a) { return __uint_as_float(lds32(a)); };
        const float ci = L(KS(cinv, r + c)), k0 = L(KS(tap0, r + c)) + (NC == 1 ? L(KS(tap0, r + 1)) : 0.f);
        const float mx = fmaxf(ci * (L(KS(kmax, r + c)) + (NC == 1 ? L(KS(kmax, r + 1)) : 0.f) + 0x1p-14f), fabsf(k0));
        const uint32_t e = min(max(__float_as_uint(mx) >> 23, 4u), 250u);
        const float s = __uint_as_float((253u - e) << 23), f = s * ci;
        if (w == 0 && lane == 0) sts32(KS(kexp, r + c), e);
        sc[c] = pack2h(f, f); t0[c] = pack2h(k0 * s, 0.f);
    }
#pragma unroll
    for (int h = 0; h < 2; h++)
#pragma unroll
        for (int j = 0; j < 4; j++) {
            const uint32_t a0 = kt + (u4(ko[h], j) & 0xFFFF), a1 = kt + (u4(ko[h], j) >> 16);
#pragma unroll
            for (int c = 0; c < 2; c++)
                asm volatile("{\n.reg .b16 a, b;\nld.shared.b16 a, [%1];\nld.shared.b16 b, [%2];\nmov.b32 %0, {a, b};\n}"
                             : "=r"(u[c][h][j]) : "r"(a0 + c * KG_RES), "r"(a1 + c * KG_RES) : "memory");
            if (NC == 1) u[0][h][j] = hadd(u[0][h][j], u[1][h][j]);
#pragma unroll
            for (int c = 0; c < NC; c++) {
                u[c][h][j] = hmul(u[c][h][j], sc[c]);
                if (h + j == 0 && w == 0 && lane == 0) u[c][0][0] = __byte_perm(t0[c], u[c][0][0], 0x7610);
            }
        }
#pragma unroll
    for (int c = 0; c < NC; c++) fft_stage<NC>(u[c], c, eo, w, lane);
}

template <int NC, bool SHEAR, class Mid>
__device__ __forceinline__ void fft_forward(const uint4 (&a1)[4], const uint4 (&tw)[4], uint32_t eo, uint32_t s2, uint32_t (&X)[NC][2][8], Mid mid) {
    uint32_t dr[8 * NC], di[8 * NC];
    const uint64_t de = mkdesc(eo, 4096, 1024, 1), d2 = mkdesc(s2, 16, 1024, 1);
    wg_fence();
    wgmma_s1(dr, a1[0], de, 0);
    wgmma_s1(di, a1[2], de + (NC == 2 ? 256 : 4), 0);
    wgmma_s1(dr, a1[1], de + 128, 1);
    wgmma_s1(di, a1[3], de + (NC == 2 ? 384 : 132), 1);
    wg_commit();
    mid();
    wg_wait<0>();
#pragma unroll
    for (int c = 0; c < NC; c++) {
        uint4 zr[2], zi[2];
#pragma unroll
        for (int p = 0; p < 2; p++)
#pragma unroll
            for (int i = 0; i < 4; i++) {
                const uint32_t r = dr[8 * c + 4 * p + i], m = di[8 * c + 4 * p + i], tr = u4(tw[p], i), ti = u4(tw[2 + p], i);
                if (SHEAR) {
                    const uint32_t r1 = hfma(tr, m, r), m1 = hfma(ti, r1, m);
                    u4r(zr[p], i) = hfma(tr, m1, r1); u4r(zi[p], i) = m1;
                } else {
                    u4r(zr[p], i) = hfms(m, ti, hmul(r, tr));
                    u4r(zi[p], i) = hfma(m, tr, hmul(r, ti));
                }
            }
        wg_fence();
        wgmma_h32_rs<0>(X[c][0], zi[0], d2 + 2, 0);
        wgmma_h32_rs<0>(X[c][1], zi[1], d2 + 6, 0);
        wgmma_h32_rs<0>(X[c][0], zr[0], d2, 1);
        wgmma_h32_rs<0>(X[c][1], zr[1], d2 + 4, 1);
        wg_commit();
    }
}

template <int NC, class Idle, class Staged>
__device__ __forceinline__ void conv_wg(int ch0, int layer, uint32_t eo, uint32_t zb, uint32_t s23, uint32_t kexp, uint32_t epoch, uint32_t st, uint32_t sbar, uint32_t fbar,
                                        int warp, int lane, uint4 (&a1)[4], uint4 (&tw)[4], Idle idle, Staged staged TS_ARG) {
    const int wg = warp >> 2, w = warp & 3, t = 32 * w + lane, mi = lane >> 3, mj = lane & 7;
    auto F = [](uint32_t x) { return __uint_as_float(x); };
    uint32_t KH[NC][2][8];
    TS(2);
    fft_forward<NC, false>(a1, tw, eo, s23, KH, [] {});
    named_bar(1 + wg, 128);
    uint4 a4[4];
#pragma unroll
    for (int i = 0; i < 4; i++) if (NC == 2) { tw[i] = ldg_tab(4 + i, t); a4[i] = ldg_tab(12 + i, t); }
    wg_wait<0>();
    TS(4);
    idle();
    uint2 x[NC][2][2];
    const uint32_t ra[2] = {4u * t, 4u * (t ^ 252)};
    auto stats = [&] {
        uint4 s[8];
        TS(1);
#pragma unroll
        for (int i = 0; i < 8; i++) s[i] = make_uint4(layer, 0, 0, 0);
        int spin = 0;
        uint32_t bad;
        do {
            bad = 0;
#pragma unroll
            for (int i = 0; i < 8; i++)
                if (((s[i].x ^ layer) & 1u) == 0) s[i] = ld_ll4((const uint4*)(g_fs[0] + ra[i >> 2] + (SEQ * (i & 1) + 1024 * ((i >> 1) & 1))));
#pragma unroll
            for (int i = 0; i < 8; i++) bad |= ~(s[i].x ^ layer);
        } while ((bad & 1u) && ++spin < (1 << 18));
#pragma unroll
        for (int i = 0; i < 8; i++) sts128(st + i * 2048 + t * 16, s[i]);
        __syncwarp();
        if (lane == 0) mbar_arrive(sbar + 8 * w);
        TS(14);
    };
    {
        const int tile = ((2 * w + (lane & 1)) ^ ((lane & 2) ? 15 : 0)) + 4 * (lane & 4);
        const bf16* pp = g_x1T + (uint32_t)(ch0 + NC - 1) * XP + 64 * tile + 60;
        uint32_t v;
        int spin = 0;
        do { asm volatile("ld.relaxed.gpu.global.u32 %0, [%1];" : "=r"(v) : "l"(pp) : "memory"); } while (__any_sync(~0u, ~(v ^ layer) & 1u) && ++spin < (1 << 18));
    }
    TS(5);
    auto xload = [&](int i) {
        const unsigned long long v = ld_ll((const unsigned long long*)(g_x1T + (uint32_t)ch0 * XP + ra[(i >> 1) & 1] + ((i >> 2) * XP + 1024 * (i & 1))));
        x[i >> 2][(i >> 1) & 1][i & 1] = make_uint2((uint32_t)v, (uint32_t)(v >> 32));
    };
#pragma unroll
    for (int i = 0; i < 4 * NC; i++) xload(i);
    TS(6);
    if (NC == 1) stats();
    for (int spin = 0; spin < (1 << 18); spin++) {
        uint32_t bad = 0;
#pragma unroll
        for (int i = 0; i < 4 * NC; i++) bad |= ~(x[i >> 2][(i >> 1) & 1][i & 1].x ^ layer);
        if (!(bad & 1u)) break;
#pragma unroll
        for (int i = 0; i < 4 * NC; i++) if (((x[i >> 2][(i >> 1) & 1][i & 1].x ^ layer) & 1u) == 0) xload(i);
    }
    __syncwarp();
#pragma unroll
    for (int i = 0; i < 4; i++) if (NC == 1) { tw[i] = ldg_tab(4 + i, t); a4[i] = ldg_tab(12 + i, t); }
    TS(26);
    if (NC == 2) mbar_wait(sbar + 8 * w, 0);
    staged();
    {
        uint4 s[2][2][2];
        uint32_t u[NC][2][4];
#pragma unroll
        for (int h = 0; h < 2; h++) {
            if (NC == 1 || h == 0) {
#pragma unroll
                for (int i = 4 * h; i < (NC == 1 ? 4 * h + 4 : 8); i++) s[i >> 2][(i >> 1) & 1][i & 1] = lds128(st + i * 2048 + t * 16);
            }
            if (h == 0) TS(7);
#pragma unroll
            for (int c = 0; c < NC; c++)
#pragma unroll
                for (int j = 0; j < 4; j++) {
                    const uint4 &a = s[h][j >> 1][0], &b = s[h][j >> 1][1];
                    const uint32_t xv = (j & 1) ? x[c][h][j >> 1].y : x[c][h][j >> 1].x;
                    u[c][h][j] = pack2h(fmaf(bf_lo(xv), F(u4(a, 2 * (j & 1))), F(u4(b, 2 * (j & 1)))), fmaf(bf_hi(xv), F(u4(a, 2 * (j & 1) + 1)), F(u4(b, 2 * (j & 1) + 1))));
                }
        }
#pragma unroll
        for (int c = 0; c < NC; c++) fft_stage<NC>(u[c], c, eo, w, lane);
    }
    TS(8);
    fence_async_smem();
    TS(9);
    named_bar(1 + wg, 128);
    uint32_t X[NC][2][8], Y[NC][2][8];
    uint32_t oscale[NC];
    fft_forward<NC, true>(a1, tw, eo, s23, X, [&] {
#pragma unroll
        for (int c = 0; c < NC; c++) oscale[c] = (lds32(kexp + 4 * c) + 3u) * 0x00800080u;
        if (layer) {
#pragma unroll
            for (int i = 0; i < 4 * NC; i++) asm volatile("mov.b32 %0, 0;\nmov.b32 %1, 0;" : "=r"(x[i >> 2][(i >> 1) & 1][i & 1].x), "=r"(x[i >> 2][(i >> 1) & 1][i & 1].y));
        }
        if (NC == 2 && wg == 1 && lane == 0) mbar_arrive(fbar);
        TS(3); if (F_STAG >= 2 && NC == 2 && wg == 1) named_bar(10 + w, 64); });
    if (F_STAG == 2 && NC == 2 && wg == 0) asm volatile("bar.arrive %0, 64;" ::"r"(10 + w) : "memory");
    TS(10);
    const uint64_t d3 = mkdesc(s23 + 4096, 16, 1024, 1);
#pragma unroll
    for (int c = 0; c < NC; c++) {
        wg_wait<NC - 1>();
        TS(11 + c);
        uint4 pr[2], pi[2];
#pragma unroll
        for (int i = 0; i < 4; i++) {
            const uint32_t er = X[c][0][i], ei = X[c][0][4 + i], orr = X[c][1][i], oi = X[c][1][4 + i];
            const uint32_t ar = KH[c][0][i], ai = KH[c][0][4 + i], br = KH[c][1][i], bi = KH[c][1][4 + i];
            u4r(pr[0], i) = hfms(bi, oi, hfma(br, orr, hfms(ai, ei, hmul(ar, er))));
            u4r(pi[0], i) = hfma(bi, orr, hfma(br, oi, hfma(ai, er, hmul(ar, ei))));
            u4r(pr[1], i) = hfms(ai, oi, hfma(ar, orr, hfms(bi, ei, hmul(br, er))));
            u4r(pi[1], i) = hfma(ai, orr, hfma(ar, oi, hfma(bi, er, hmul(br, ei))));
        }
        if (F_STAG == 3 + c && NC == 2 && wg == 0) asm volatile("bar.arrive %0, 64;" ::"r"(10 + w), "r"(pr[0].x ^ pr[1].w ^ pi[0].y ^ pi[1].z) : "memory");
        wg_fence();
        wgmma_h32_rs<0>(Y[c][0], pr[0], d3, 0);
        wgmma_h32_rs<0>(Y[c][1], pr[1], d3 + 4, 0);
        wgmma_h32_rs<0>(Y[c][0], pi[0], d3 + 2, 1);
        wgmma_h32_rs<0>(Y[c][1], pi[1], d3 + 6, 1);
        wg_commit();
    }
#pragma unroll
    for (int c = 0; c < NC; c++) {
        if (c + 1 < NC) wg_wait<1>(); else wg_wait<0>();
        TS(13 + c);
        uint32_t zr[2][4], zi[2][4];
#pragma unroll
        for (int p = 0; p < 2; p++)
#pragma unroll
            for (int i = 0; i < 4; i++) {
                const uint32_t r = Y[c][p][i], m = Y[c][p][4 + i], tr = u4(tw[p], i), ti = u4(tw[2 + p], i);
                const uint32_t r1 = hfms(tr, m, r), m1 = hfms(ti, r1, m);
                zr[i & 1][2 * p + (i >> 1)] = hfms(tr, m1, r1);
                zi[i & 1][2 * p + (i >> 1)] = m1;
            }
        const int kr = 4 * (mj >> 1) + (mj & 1) + 2 * (mj >> 2), ki = kr ^ 2;
#pragma unroll
        for (int h = 0; h < 2; h++) {
            const uint32_t a = zb + (2 * w + h) * 2048;
            stsm_x4(a + ki * 128 + (((4 * c + mi) ^ (ki & 7)) << 4), zi[h][0], zi[h][1], zi[h][2], zi[h][3]);
            stsm_x4(a + kr * 128 + (((4 * c + mi) ^ (kr & 7)) << 4), zr[h][0], zr[h][1], zr[h][2], zr[h][3]);
        }
    }
    TS(15);
    fence_async_smem();
    TS(16);
    named_bar(1 + wg, 128);
    TS(17);
    float acc[16 * NC];
    const uint64_t dz = mkdesc(zb, 4096, 1024, 1);
    wg_fence();
#pragma unroll
    for (int ks = 0; ks < 4; ks++) wgmma_s4(acc, a4[ks], dz + ks * 256, 0x44EEEE44u, ks > 0);
    wg_commit();
    const uint32_t fb = ~lds32(epoch);
    uint32_t mk[NC][2][4];
    const char* dst[2];
    {
        uint32_t l2;
        asm volatile("mov.u32 %0, %%laneid;" : "=r"(l2));
        const char* base = layer ? (const char*)g_of + (uint32_t)(ch0 / 80) * 327680u + (uint32_t)(ch0 % 80) * 256u : (const char*)g_x2T + (uint32_t)ch0 * (XP * 2u);
        const uint32_t k0 = layer ? 8 : (ch0 >> 1) & 3;
        uint32_t m0[2] = {k0 == 2 * (l2 & 3), k0 == 2 * (l2 & 3) + 1}, m1[2][2];
#pragma unroll
        for (int h = 0; h < 2; h++) {
            const uint32_t v = (32 * w + l2) ^ (h ? 252u : 0u);
            dst[h] = base + (layer ? (v >> 4) * 20480u + (v & 15u) * 16u : v * 8u);
            m1[h][0] = m0[0] | (~(v >> 3) & layer); m1[h][1] = m0[1] | ((v >> 3) & layer);
            asm volatile("" : "+l"(dst[h]), "+r"(m1[h][0]), "+r"(m1[h][1]), "+r"(m0[h]), "+r"(oscale[h % NC]));
        }
#pragma unroll
        for (int i = 0; i < 8 * NC; i++) {
            const int c = i >> 3, h = (i >> 2) & 1, j = i & 3;
            mk[c][h][j] = (j >> 1) == (NC == 2 ? c : ch0 & 1) ? m1[h][j & 1] : m0[j & 1];
            if (NC == 1) asm volatile("" : "+r"(mk[c][h][j]));
        }
        mbar_wait(sbar, 0);
    }
    auto mark = [&](uint32_t v, uint32_t m) { return (v & ~m) | (fb & m); };
    wg_wait<0>();
    TS(18);
#pragma unroll
    for (int c = 0; c < NC; c++) {
        uint32_t r[2][4];
#pragma unroll
        for (int j = 0; j < 4; j++) {
            const float* d = acc + 4 * (4 * c + j);
            const uint32_t y0 = pack2(d[0] + d[2], d[1] + d[3]), y1 = pack2(d[0] - d[2], d[1] - d[3]);
            asm("fma.rn.bf16x2 %0, %1, %2, %3;" : "=r"(r[0][j]) : "r"(y0), "r"(oscale[c]), "r"((j & 1) ? x[c][0][j >> 1].y : x[c][0][j >> 1].x));
            asm("fma.rn.bf16x2 %0, %1, %2, %3;" : "=r"(r[1][j]) : "r"(y1), "r"(oscale[c]), "r"((j & 1) ? x[c][1][j >> 1].y : x[c][1][j >> 1].x));
        }
#pragma unroll
        for (int h = 0; h < 2; h++)
            asm volatile("{\n.reg .pred p;\n.reg .b128 t;\n.reg .b64 a, b;\nsetp.ne.u32 p, %5, 0;\nmov.b64 a, {%1, %2};\nmov.b64 b, {%3, %4};\nmov.b128 t, {a, b};\n"
                         "@p st.relaxed.gpu.global.b128 [%0], t;\n@!p st.relaxed.gpu.global.b64 [%6], a;\n@!p st.relaxed.gpu.global.b64 [%6 + 2048], b;\n}"
                         ::"l"(dst[h] + c * 256), "r"(mark(r[h][0], mk[c][h][0])), "r"(mark(r[h][1], mk[c][h][1])), "r"(mark(r[h][2], mk[c][h][2])), "r"(mark(r[h][3], mk[c][h][3])), "r"(layer), "l"(dst[h] + c * XP * 2) : "memory");
    }
    if (layer == 0 && lane == 0) asm volatile("red.relaxed.gpu.global.add.u32 [%0], %1;" ::"l"(g_xcnt[ch0 >> 6][w]), "n"(NC) : "memory");
    TS(19);
}

#define Q_S0 8
#define R_CONS 192
#define K_CSUN 1
constexpr int K_CSU = K_CSUN;
#define G_MAP 1
constexpr int Q_SP = 4;
#define A_VLO 4
constexpr int Q_ST = 4;
constexpr int Q_AB = 16384, Q_BB = 30720, Q_SB = Q_AB + Q_BB;
constexpr int Q_EROW = 336;
constexpr int Q_ESLOT = 8 * Q_EROW;
constexpr int Q_EOFF = Q_ST * Q_SB;
constexpr int Q_KG = 2 * Q_SB;
static_assert(3 * Q_ESLOT <= 8192 && Q_KG + KG_TABLES <= Q_EOFF + 4096, "exchange slots, kernel generation");
constexpr int F_EO = Q_EOFF, F_S23 = F_EO + 2 * 8192 + 4096, Q_KDUMP = F_S23 + 8192;
constexpr int Q_MISC = Q_KDUMP + 6 * KG_RES;
__host__ __device__ constexpr int w_grp(int j) { return j < 7 ? 2 * Q_SB + 4096 + j * 12800 : 0; }
constexpr int W_RES = Q_AB;
__device__ __forceinline__ int o_slot(int wg, int s) { return W_RES + (((2 * s + 2) & 7) + wg) * 10240; }
__device__ __forceinline__ int w_out(int wg) { return W_RES + (2 + 3 * wg) * 10240; }
static_assert(W_RES + 8 * 10240 == w_grp(0) && w_grp(6) + 12800 <= Q_EOFF && w_grp(3) <= 3 * Q_SB, "phase W layout");

constexpr int Q_WOT = Q_EOFF + 4096;

__device__ unsigned g_epoch;
__device__ __align__(1024) unsigned g_bar[4][16][32];
__device__ __align__(1024) uint4 g_wop[8][80][10][8];
__device__ __align__(1024) uint4 g_csp[8][16][96];
__device__ __align__(1024) uint4 g_stp[16][8][64];
__device__ __align__(1024) uint4 g_sp2[16][8][8][8];
__device__ __align__(1024) uint4 g_halo[128][2][5][32];

struct Bars { uint64_t full[Q_ST], empty[Q_ST], wfull[3], ex[7], res, go, qdone, prep, hdone, idx, fdone0, att[2], wfree, soon[2], fdone1, st[4], kfree, staged, xland[4], spec; };
constexpr int NBAR = sizeof(Bars) / 8;
struct OBars { uint64_t full[8], ready[8], empty[8]; };
struct Misc { float cs[240], mean[2][64], rstd[2][72]; Bars bar[2]; OBars ob; KgShared kg; uint32_t epoch, pad; };
#define MISC(f) (sb + Q_MISC + (uint32_t)offsetof(Misc, f))
constexpr int Q_SMEM = Q_MISC + sizeof(Misc) + TS_SMEM;
__host__ __device__ constexpr int bar_count(int i) {
#define BAR_IS(f) (i == offsetof(Bars, f) / 8)
    return (i >= 4 && i < 8) ? 16 : (BAR_IS(go) || (i >= offsetof(Bars, att) / 8 && i < offsetof(Bars, st) / 8)) ? 4 : (BAR_IS(qdone) || BAR_IS(fdone0)) ? 8 : BAR_IS(prep) ? 96 :
           BAR_IS(hdone) ? 6 : BAR_IS(kfree) ? 24 : BAR_IS(staged) ? 2 : 1;
}
__device__ __forceinline__ void grid_wait(const unsigned* c, int n, unsigned target, int lane) {
    const unsigned* p = c + 32 * min(lane, n - 1);
    unsigned v;
    int spin = 0;
    do { asm volatile("ld.relaxed.gpu.global.u32 %0, [%1];" : "=r"(v) : "l"(p) : "memory"); } while (!__all_sync(~0u, (int)(v - target) >= 0) && ++spin < (1 << 18));
    fence_acquire();
}
__device__ __forceinline__ void grid_arrive(unsigned* c) {
    fence_release();
    asm volatile("red.relaxed.gpu.global.add.u32 [%0], 1;" ::"l"(c) : "memory");
}

#define TMAP(n) ([] { const CUtensorMap* p_; asm volatile("{\n.reg .b64 t;\nmov.b64 t, fused_kernel_param_" #n ";\ncvta.param.u64 %0, t;\n}" : "=l"(p_)); return p_; }())
extern "C" __global__ void __launch_bounds__(384, 1)
fused_kernel(const SsmParams sp, const __grid_constant__ CUtensorMap mX0, const __grid_constant__ CUtensorMap mX1, const __grid_constant__ CUtensorMap mW,
             const __grid_constant__ CUtensorMap mWr,
             const __grid_constant__ CUtensorMap mRes0, const __grid_constant__ CUtensorMap mRes1, const __grid_constant__ CUtensorMap mOut,
             const __grid_constant__ CUtensorMap mWo, const __grid_constant__ CUtensorMap mFin, const __grid_constant__ CUtensorMap mResA) {
    extern __shared__ __align__(1024) char smraw[];
    const uint32_t sb = s2u(smraw);
    int tid, warp, lane, bx, rank, blk, hg, rot, c0;
    int role;
    {
        const int c = blockIdx.x >> 1, d = c - 41, r = d >= 21 ? 3 : d >= 14 ? 2 : d >= 7 ? 1 : 0;
        const int gp = c < 4 ? 0 : c <= 40 ? (c + 7) & 7 : d - 7 * r + 1;
        const int k = c < 4 ? c : c <= 40 ? (c >> 3) + (gp == 0 ? 3 : gp >= 3 && gp < 7 ? 0 : -1) : (gp >= 3 ? 5 : 4) + r;
        role = G_MAP == 1 ? 16 * k + 2 * gp + (blockIdx.x & 1) : G_MAP == 2 ? 16 * gp + 2 * k + (blockIdx.x & 1) : blockIdx.x;
    }
    auto indices = [&] {
        asm volatile("mov.u32 %0, %%tid.x;" : "=r"(tid));
        asm volatile("mov.u32 %0, %1;" : "=r"(bx) : "r"(role));
        warp = __shfl_sync(~0u, tid >> 5, 0); lane = tid & 31;
        rank = bx & 1; blk = bx & 15; hg = bx >> 4;
        const int u = ((blk >> 1) + hg) & 7;
        rot = (5 * u) >> 2; c0 = 16 * (u & 3);
    };
    indices();
    TS_DECL;
    TS_BEGIN;
#define EPOCH lds32(MISC(epoch))
    int layer = 0;
    uint32_t bars = MISC(bar);
#define BAR(f) (bars + (uint32_t)offsetof(Bars, f))
    auto chunk = [&](int it, int s0) {
        const int i = it < s0 ? it : it - 2;
        return (it >> 1) == (s0 >> 1) ? rot + (it & 1) : i < rot ? i : i + 2;
    };
    auto osrc_of = [&](int j) { return j == 0 ? hg : j - 1 < hg ? j - 1 : j; };
    auto issue_w = [&](uint32_t bb, int it, int lay) {
        const int half = rank;
        const int s = it & (Q_ST - 1);
        const uint32_t fb = bb + 8 * s, db = sb + s * Q_SB + Q_AB + half * 15360;
        const int k0 = chunk(it, Q_SP * lay) * 64 + half * 32;
#pragma unroll
        for (int p = 0; p < 3; p++) tma2d_mc(db + p * 4096, TMAP(3), p * DM + hg * 80, k0, fb, 3);
        tma3d_mc(db + 12288, TMAP(4), hg * 80 + 64, k0, 0, fb, 3);
    };
    auto issue_x = [&](int it) {
        const int s = it & (Q_ST - 1), kc = chunk(it, Q_SP * layer);
        mbar_expect(BAR(full) + 8 * s, Q_SB);
        tma3d(sb + s * Q_SB, TMAP(1) + layer, (layer ? blk : kc) * 64, (layer ? kc : blk) * 64, 0, BAR(full) + 8 * s);
    };
    {
        KgParams kp;
        const uint32_t epoch0 = ldg32(sp.epoch);
        kgen_load(kp, bx, warp, lane, sp);
        if (warp < 8) {
            cluster_arrive_relaxed();
        } else {
            if (elect_one()) {
                if (warp < 10) { prefetch_tmap(TMAP(3)); prefetch_tmap(TMAP(4)); } else prefetch_tmap(warp == 10 ? TMAP(1) : TMAP(8));
                const uint32_t b0 = bars + (warp >= 10 ? sizeof(Bars) : 0);
                if (warp & 1) {
#pragma unroll
                    for (int i = 0; i < NBAR / 2; i++) mbar_init(b0 + i * 8, bar_count(i));
                } else {
#pragma unroll
                    for (int i = NBAR / 2; i < NBAR; i++) mbar_init(b0 + i * 8, bar_count(i));
                }
                fence_mbar_init();
            }
            __syncwarp();
            cluster_arrive_relaxed();
            TS(29);
            cluster_wait();
            TS(27);
            if (elect_one()) {
                if (warp < 10) {
                    issue_w(BAR(full), warp - 8, 0);
                } else if (warp == 10) {
                    issue_x(0); issue_x(1);
                    prefetch_l2((const char*)c_fft + bx * (sizeof(c_fft) / 128), sizeof(c_fft) / 128);
                } else {
                    mbar_expect(BAR(idx), 8192 + 6400);
                    asm volatile("cp.async.bulk.tensor.4d.shared::cluster.global.mbarrier::complete_tx::bytes [%0], [%1, {0, 0, %3, %4}], [%2];"
                                 ::"r"(sb + Q_WOT), "l"(TMAP(8)), "r"(BAR(idx)), "r"(10 * hg), "r"(5 * blk) : "memory");
                    bulk_g2s(sb + F_S23, c_fft + 18 * 512, 8192, BAR(idx));
                }
            }
            __syncwarp();
            TS(30);
        }
        indices();
        kgen_tables(kp, sb + Q_KG, sb + Q_KDUMP, MISC(kg), warp, lane, [&] { if (warp < 8) cluster_wait(); } TS_PASS);
        __syncwarp();
        if (lane == 0) { mbar_arrive_cta(BAR(kfree), 0); mbar_arrive_cta(BAR(kfree), 1); }
        if (warp >= 8) {
            const int t2 = tid - 256;
            float csum[10];
            if (warp < 11 && elect_one()) {
#pragma unroll
                for (int i = 0; i < 8; i++) mbar_init(MISC(ob) + (warp - 8) * 64 + i * 8, warp == 10 ? 4 : 1);
                fence_mbar_init();
            }
            __syncwarp();
            if (t2 == 0) sts32(MISC(epoch), epoch0);
            if (t2 < 64) stg128(&g_sp2[blk][hg][0][0] + t2, make_uint4(0, 0, 0, 0));
            if (t2 >= 64 && t2 < 80) stg128(&g_of[hg][blk][640 * ((t2 >> 3) & 1) + 8 * (73 + (t2 & 6)) + 6 + (t2 & 1)], make_uint4(epoch0, epoch0, epoch0, epoch0));
            if (t2 >= 120) stg128((uint4*)g_fs + 8 * bx + t2 - 120, make_uint4(0, 0, 0, 0));
#pragma unroll
            for (int i = 0; i < 2; i++)
                if (t2 + 128 * i < 192) stg128(g_x1T + (uint32_t)cta_channel(bx, 4 * i + 1 + 2 * (t2 >> 6)) * XP + 32 * (t2 & 62) + 48 + 8 * (t2 & 1), make_uint4(0, 0, 0, 0));
#pragma unroll
            for (int i = 0; i < 3; i++)
                if (t2 + 128 * i < 320) stg128(&g_halo[bx][0][0][0] + t2 + 128 * i, make_uint4(0, 0, 0, 0));
            named_bar(13, 128);
            if (warp > 8) {
                const int hw = warp - 9, mi = lane >> 3, mj = lane & 7;
                mbar_wait(BAR(idx), 0);
                if (hw == 2 && elect_one()) { bulk_s2g(&g_wop[hg][5 * blk], sb + Q_WOT, 6400); bulk_commit(); }
                __syncwarp();
                mbar_wait(BAR(full), 0);
                mbar_wait(BAR(full) + 8, 0);
#pragma unroll
                for (int f = 0; f < 10; f++) csum[f] = 0.f;
#pragma unroll K_CSU
                for (int G = 0; G < 5; G++) {
                    const int row = c0 + 40 * rank + 8 * G + mj;
                    const uint32_t b = sb + (row >> 6) * Q_SB + Q_AB + ((row >> 5) & 1) * 15360;
                    uint32_t r[10];
                    ldsm_x4_t(r[0], r[1], r[2], r[3], b + hw * 4096 + (row & 31) * 128 + ((mi ^ mj) << 4));
                    ldsm_x4_t(r[4], r[5], r[6], r[7], b + hw * 4096 + (row & 31) * 128 + (((4 + mi) ^ mj) << 4));
                    ldsm_x2_t(r[8], r[9], b + 12288 + hw * 1024 + (row & 31) * 32 + (((mi & 1) ^ (mj >> 2)) << 4));
#pragma unroll
                    for (int f = 0; f < 10; f++) csum[f] += bf_lo(r[f]) + bf_hi(r[f]);
                }
                const int q = lane & 3;
                float t[3];
#pragma unroll
                for (int j = 0; j < 3; j++) {
                    float v[4];
#pragma unroll
                    for (int k = 0; k < 4; k++) v[k] = 4 * j + k < 10 ? csum[4 * j + k] : 0.f;
                    const float a0 = ((q & 2) ? v[2] : v[0]) + __shfl_xor_sync(~0u, (q & 2) ? v[0] : v[2], 2);
                    const float a1 = ((q & 2) ? v[3] : v[1]) + __shfl_xor_sync(~0u, (q & 2) ? v[1] : v[3], 2);
                    t[j] = ((q & 1) ? a1 : a0) + __shfl_xor_sync(~0u, (q & 1) ? a0 : a1, 1);
                }
                st_ll4(&g_csp[hg][blk][tid - 288], ~EPOCH & 1u, __float_as_uint(t[0]), __float_as_uint(t[1]), __float_as_uint(t[2]));
            }
        }
        TS(1);
    }

    uint4 fa1[4], ftw[4];
    auto conv_tables = [&] {
#pragma unroll
        for (int i = 0; i < 4; i++) { fa1[i] = ldg_tab(i, tid & 127); ftw[i] = ldg_tab(8 + i, tid & 127); }
    };
    if (warp >= 8) {
    asm volatile("setmaxnreg.dec.sync.aligned.u32 %0;" ::"n"(504 - 2 * R_CONS));
    uint32_t ophase = 0;
#pragma unroll 1
    for (; layer < 2; layer++, bars += sizeof(Bars)) {
        indices();
        TS_PHASE(2 * layer);
        if (layer) {
            const int i = warp - 8, g = lane >> 2;
            const uint32_t eb = ~EPOCH, a = sb + i * Q_SB + g * 128 + (((2 * (lane & 3)) ^ g) << 4) + 2 * (g & 6);
            const unsigned* pp = g_xcnt[chunk(i, Q_SP)][(blk < 8 ? blk : 15 - blk) >> 1];
            mbar_wait(BAR(fdone0) - sizeof(Bars), 0);
            if (i == 3) mbar_wait(BAR(fdone1) - sizeof(Bars), 0);
            if (i == 3 && elect_one()) grid_arrive(g_bar[2][hg]);
            __syncwarp();
            uint32_t bad;
            int spin = 0;
            do { asm volatile("ld.relaxed.gpu.global.u32 %0, [%1];" : "=r"(bad) : "l"(pp) : "memory"); } while ((int)(bad + 64 * eb) < 0 && ++spin < (1 << 18));
            fence_async_global();
            TS(1);
            spin = 0;
            do {
                if (elect_one()) {
                    mbar_expect(BAR(xland) + 8 * i, Q_AB);
                    tma3d(sb + i * Q_SB, TMAP(2), blk * 64, chunk(i, Q_SP) * 64, 0, BAR(xland) + 8 * i);
                }
                __syncwarp();
                mbar_wait(BAR(xland) + 8 * i, spin & 1);
                bad = 0;
#pragma unroll
                for (int k = 0; k < 16; k++) bad |= lds32(a + k * 1024) ^ eb;
            } while (__any_sync(~0u, bad & 1u) && ++spin < (1 << 16));
            if (lane == 0) mbar_expect(BAR(full) + 8 * i, Q_BB);
            TS(9);
        }
        if (warp == 8) {
            if (layer) {
                grid_wait(g_bar[2][0], 8, 16 * (EPOCH + 1), lane);
                fence_async_global();
                TS(10);
            }
            if (elect_one()) {
#pragma unroll 1
                for (int it = 2 + 2 * layer; it < 10; it++) {
                    if (it >= Q_ST) mbar_wait(BAR(empty) + 8 * (it & (Q_ST - 1)), ((it >> 2) - 1) & 1);
                    else mbar_wait(BAR(kfree), 0);
                    if (it == Q_ST + Q_SP * layer) mbar_wait(BAR(hdone), 0);
                    issue_x(it);
                    issue_w(BAR(full), it, layer);
                    if (it == Q_SP + 1) mbar_arrive(BAR(spec));
                }
                { prefetch_tmap(TMAP(5) + layer); prefetch_tmap(TMAP(7)); prefetch_tmap(TMAP(10)); }
                if (layer == 0) { mbar_wait(BAR(prep), 0); fence_async_global(); }
#pragma unroll 1
                for (int j = 0; j < 8; j++) {
                    const int b = (j + 1) >> 2;
                    const uint32_t fb = BAR(wfull) + 8 * b;
                    if (j == 0 || j == 3 || j == 7) {
                        mbar_wait(BAR(empty) + 8 * ((2 + b) & 3), b < 2);
                        TS(11 + b);
                        mbar_expect(fb, (b == 0 ? 3 : b == 1 ? 4 : 1) * 12800);
                    }
                    bulk_g2s_mc(sb + w_grp(j) + rank * 6400, &g_wop[hg][osrc_of(j) * 10 + rank * 5], 6400, fb, 3);
                }
                mbar_expect(BAR(res), 20480);
                if (layer) {
                    tma3d(sb + W_RES, TMAP(6), blk * 64, hg * 80, 0, BAR(res));
                } else {
#pragma unroll 1
                    for (int p = 0; p < 2; p++) {
                        tma3d(sb + W_RES + p * 10240, TMAP(10), hg * 80, blk * 64, p, BAR(res));
                        tma3d(sb + W_RES + p * 10240 + 8192, TMAP(5), hg * 80 + 64, blk * 64, p, BAR(res));
                    }
                }
            }
            __syncwarp();
        } else {
            const int ht = tid - 288, hw = warp - 9, mi = lane >> 3, mj = lane & 7, g = lane >> 2, q = lane & 3;
            auto F = [](uint32_t x) { return __uint_as_float(x); };
            auto U = [](float x) { return __float_as_uint(x); };
            const uint32_t lb = layer ^ 1, eb = ~EPOCH & 1u;
            if (layer) mbar_wait(BAR(spec), 0);
            mbar_wait(BAR(full), layer);
            mbar_wait(BAR(full) + 8, layer);
            if (ht == 0) TSX(2, 2);
            uint32_t xf[3][20];
#pragma unroll
            for (int i = 0; i < 3; i++) {
                const int tile = min(hw + 3 * i, 7);
#pragma unroll
                for (int k = 0; k < 5; k++) {
                    const int ch = c0 + 16 * k + 8 * (mi >> 1), tok = 16 * (tile & 3) + 8 * (mi & 1);
                    const uint32_t a = sb + (ch >> 6) * Q_SB + (tile >> 2) * 8192;
                    if (layer == 0) ldsm_x4(xf[i][4 * k], xf[i][4 * k + 1], xf[i][4 * k + 2], xf[i][4 * k + 3], a + (tok + mj) * 128 + ((((ch & 63) >> 3) ^ mj) << 4));
                    else ldsm_x4_t(xf[i][4 * k], xf[i][4 * k + 1], xf[i][4 * k + 2], xf[i][4 * k + 3], a + ((ch & 63) + mj) * 128 + (((tok >> 3) ^ mj) << 4));
                }
            }
            fence_async_smem();
            __syncwarp();
            if (lane == 0) { mbar_arrive_cta(BAR(hdone), 0); mbar_arrive_cta(BAR(hdone), 1); }
            if (ht == 0) TSX(2, 3);
            if (layer == 0) {
                if (hw == 2 && elect_one()) { bulk_wait(); fence_async_global(); grid_arrive(g_bar[3][hg]); }
                __syncwarp();
                mbar_wait(BAR(kfree), 0);
            }
            if (ht == 0) TSX(2, 8);
#pragma unroll 1
            for (int tile = hw; tile < 8; tile += 3) {
                float a[4] = {0.f, 0.f, 0.f, 0.f};
#pragma unroll
                for (int j = 0; j < 20; j++) {
                    const float lo = bf_lo(xf[0][j]), hi = bf_hi(xf[0][j]);
                    a[2 * (j & 1)] += lo + hi; a[2 * (j & 1) + 1] = fmaf(lo, lo, fmaf(hi, hi, a[2 * (j & 1) + 1]));
                    xf[0][j] = xf[1][j]; xf[1][j] = xf[2][j];
                }
#pragma unroll
                for (int j = 0; j < 4; j++) { a[j] += __shfl_xor_sync(~0u, a[j], 1); a[j] += __shfl_xor_sync(~0u, a[j], 2); }
                if (q == 0) st_ll4(&g_stp[blk][hg][8 * tile + g], (U(a[0]) & ~1u) | lb, U(a[1]), U(a[2]), U(a[3]));
            }
            if (ht == 0) TSX(2, 4);
            if (layer == 0) {
                float t[4] = {0.f, 0.f, 0.f, 0.f};
                uint4 v[16];
                int spin = 0;
                uint32_t bad;
                do {
                    bad = 0;
#pragma unroll
                    for (int j = 0; j < 16; j++) v[j] = ld_ll4(&g_csp[hg][j][ht]);
#pragma unroll
                    for (int j = 0; j < 16; j++) bad |= v[j].x ^ eb;
                } while ((bad & 1u) && ++spin < (1 << 18));
#pragma unroll
                for (int j = 0; j < 16; j++) { t[0] += F(v[j].y); t[1] += F(v[j].z); t[2] += F(v[j].w); }
#pragma unroll
                for (int j = 0; j < 3; j++) if (q + 4 * j < 10) sts32(MISC(cs) + 4 * (80 * hw + 20 * (g >> 1) + 2 * (q + 4 * j) + (g & 1)), U(t[j]));
                if (hw == 2) grid_wait(g_bar[3][0], 8, 16 * (EPOCH + 1), lane);
            }
            if (ht == 0) TSX(2, 15);
            if (ht < 80) {
                const bool halo = ht >= 64;
                const int p = halo ? (ht >> 3) & 1 : ht >> 5, i = halo ? (ht & 7) - 8 : 8 + 2 * (ht & 24) + (ht & 7);
                const uint4* src = &g_stp[halo && blk ? blk - 1 : blk][0][halo ? 32 * p + 24 + (ht & 7) : ht];
                uint4 v[8];
                int spin = 0;
                uint32_t bad;
                do {
                    bad = 0;
#pragma unroll
                    for (int j = 0; j < 8; j++) v[j] = ld_ll4(src + 64 * j);
#pragma unroll
                    for (int j = 0; j < 8; j++) bad |= v[j].x ^ lb;
                } while ((bad & 1u) && ++spin < (1 << 18));
                float t[4] = {0.f, 0.f, 0.f, 0.f};
#pragma unroll
                for (int j = 0; j < 8; j++) { t[0] += F(v[j].x); t[1] += F(v[j].y); t[2] += F(v[j].z); t[3] += F(v[j].w); }
                const uint32_t s0 = ln_finish_packed(t[0], t[1]), s1 = ln_finish_packed(t[2], t[3]);
                const uint32_t am = MISC(mean) + 4 * (64 * p + i), ar = MISC(rstd) + 4 * (72 * p + i);
                if (!halo) { sts32(am - 32, U(bf_hi(s0))); sts32(am, U(bf_hi(s1))); sts32(ar, U(frcp(bf_lo(s0)))); }
                sts32(ar + 32, U(frcp(bf_lo(s1))));
            }
            fence_acquire();
            mbar_arrive(BAR(prep));
            if (ht == 0) TSX(2, 5);
        }
        __syncwarp();
        indices();
        {
            const uint4 ko[2] = {ldg_tab(16, tid & 127), ldg_tab(17, tid & 127)};
            conv_tables();
            kernel_stage<1>(ko, sb + Q_KDUMP + 4 * KG_RES, MISC(kg), 4, sb + F_EO + 2 * 8192, warp & 3, lane);
            fence_async_smem();
        }
        {
            const int p = warp & 1;
            const uint32_t fb = EPOCH ^ layer ^ 1, ob = MISC(ob) + 32 * p;
            auto fetch = [&](int j) {
                if (elect_one()) {
                    mbar_expect(ob + 8 * ((j - 1) & 3), 10240);
                    bulk_g2s(sb + o_slot(p, (j - 1) & 3), &g_of[osrc_of(j)][blk][640 * p], 10240, ob + 8 * ((j - 1) & 3));
                }
                __syncwarp();
            };
            if (warp < 10) {
                const uint32_t* pp = &g_of[osrc_of(1 + min(lane >> 2, 6))][blk][640 * p + 8 * (73 + 2 * (lane & 3)) + 7].x + 1 + 2 * (lane & 1);
                mbar_wait(BAR(qdone), 0);
                mbar_wait(BAR(att) + 8 * p, 0);
                uint32_t miss = ~0u;
                int spin = 0;
#pragma unroll 1
                for (int j = 1; j < 8; j++) {
                    while (((miss >> (4 * j - 4)) & 15u) && ++spin < (1 << 18)) {
                        uint32_t v;
                        asm volatile("ld.relaxed.gpu.global.u32 %0, [%1];" : "=r"(v) : "l"(pp) : "memory");
                        miss = __ballot_sync(~0u, (v ^ fb) & 1u);
                        fence_async_global();
                    }
                    if (j == 1) TS(16);
                    if (j > 3) mbar_wait(ob + 128 + 8 * ((j - 1) & 3), layer);
                    fetch(j);
                }
                TS(17);
            } else {
#pragma unroll 1
                for (int j = 1, spin = 0; j < 8;) {
                    const int s = (j - 1) & 3;
                    mbar_wait(ob + 8 * s, (ophase >> s) & 1);
                    ophase ^= 1u << s;
                    const uint32_t a = sb + o_slot(p, s) + (lane >> 2) * 132 + (lane & 3) * 32;
                    uint32_t bad = 0;
#pragma unroll
                    for (int i = 0; i < 10; i++) bad |= lds32(a + i * 1024) ^ fb;
                    if (__any_sync(~0u, bad & 1u) && ++spin < (1 << 16)) { fetch(j); continue; }
                    if (lane == 0) mbar_arrive(ob + 64 + 8 * s);
                    j++;
                }
            }
        }
        TS_PHASE(2 * layer + 1);
        TS(0);
        indices();
        named_bar(3, 128);
        conv_wg<1>(cta_channel(bx, 4), layer, sb + F_EO + 2 * 8192, sb + 2 * Q_SB, sb + F_S23, MISC(kg.kexp) + 16, MISC(epoch), sb, BAR(st), 0,
                   warp, lane, fa1, ftw,
        [&] {
            if (warp == 9) {
                auto F = [](uint32_t x) { return __uint_as_float(x); };
                mbar_wait(BAR(soon) + 8 * (hg >> 2), 0);
                TS(23);
                const uint4* src = &g_sp2[blk][hg][0][0] + lane;
                uint4* dst = (uint4*)(g_fs[(lane >> 2) & 1] + 1024 * (hg >> 2) + 64 * blk + 16 * (hg & 3)) + (lane & 3);
                const bool up = lane & 8;
#pragma unroll 1
                for (int spin = 0; spin < (1 << 18); spin++) {
                    const uint4 a = ld_ll4(src), b = ld_ll4(src + 32);
                    const bool ok = !__any_sync(~0u, ~((a.x ^ layer) & (b.x ^ layer)) & 1u);
                    const float s0 = F(a.x) + F(b.x), q0 = F(a.y) + F(b.y), s1 = F(a.z) + F(b.z), q1 = F(a.w) + F(b.w);
                    float sm = (up ? s1 : s0) + __shfl_xor_sync(~0u, up ? s0 : s1, 8), sq = (up ? q1 : q0) + __shfl_xor_sync(~0u, up ? q0 : q1, 8);
                    sm += __shfl_xor_sync(~0u, sm, 16); sq += __shfl_xor_sync(~0u, sq, 16);
                    const float m = sm * (1.0f / DM), r = frsq(fmaxf(fmaf(sq, 1.0f / DM, fmaf(-m, m, 1e-5f)), 1e-5f));
                    const uint32_t v = __float_as_uint(lane & 16 ? -m * r : r);
                    const uint32_t v0 = __shfl_sync(~0u, v, 4 * lane), v1 = __shfl_sync(~0u, v, 4 * lane + 1), v2 = __shfl_sync(~0u, v, 4 * lane + 2), v3 = __shfl_sync(~0u, v, 4 * lane + 3);
                    if (ok && lane < 8) st_ll4(dst, (v0 & ~1u) | (layer ^ 1), v1, v2, v3);
                    if (ok) break;
                }
            }
            TS(25);
            mbar_wait(BAR(staged), 0);
        }, [&] {
            if (tid == 352) prefetch_tmap(layer ? TMAP(9) : TMAP(2));
        } TS_PASS);
        named_bar(3, 128);
        TS(20);
    }
    } else {
#pragma unroll 1
    for (; layer < 2; layer++, bars += sizeof(Bars)) {
    indices();
    TS_PHASE(2 * layer);
    const int wg = warp >> 2, w = warp & 3;
    const int mi = lane >> 3, mj = lane & 7, g = lane >> 2, q = lane & 3;
    TS(2);
    float acc[120];
#pragma unroll
    for (int i = 0; i < 120; i++) acc[i] = 0.f;
    auto release = [&](int it) {
        if (lane == 0) { mbar_arrive_cta(BAR(empty) + 8 * (it & (Q_ST - 1)), 0); mbar_arrive_cta(BAR(empty) + 8 * (it & (Q_ST - 1)), 1); }
    };
#pragma unroll 1
    for (int it = 0; it < 10; it++) {
        const int s = it & (Q_ST - 1);
        const uint32_t st = sb + s * Q_SB;
        const bool hold = wg == 1 && it == Q_S0;
        if (hold) {
            wg_wait<0>();
            release(it - 1);
            mbar_wait(BAR(go), 0);
        }
        mbar_wait(BAR(full) + 8 * (s), (it >> 2) & 1);
        if (it < 2) TS(3 + it);
        if (it == 6) TS(5);
        if (it == 9) TS(6);
        const uint64_t da = mkdesc(st + wg * 8192, 16, 1024, 1);
        const uint64_t db = mkdesc(st + Q_AB, 4096, 1024, 1);
        const uint64_t dr = mkdesc(st + Q_AB + 12288, 1024, 256, 3);
        if (layer == 0) {
            wg_fence();
#pragma unroll
            for (int ks = 0; ks < 4; ks++) {
                const int sc = 1;
                wgmma_n192<0, 1>(*(float(*)[96]) & acc[0], da + ks * 2, db + (ks >> 1) * 960 + (ks & 1) * 128, sc);
                wgmma_n48<0, 1>(*(float(*)[24]) & acc[96], da + ks * 2, dr + (ks >> 1) * 960 + (ks & 1) * 32, sc);
            }
            wg_commit();
        } else {
            wg_fence();
#pragma unroll
            for (int ks = 0; ks < 4; ks++) {
                const int sc = 1;
                wgmma_n192<1, 1>(*(float(*)[96]) & acc[0], da + ks * 128, db + (ks >> 1) * 960 + (ks & 1) * 128, sc);
                wgmma_n48<1, 1>(*(float(*)[24]) & acc[96], da + ks * 128, dr + (ks >> 1) * 960 + (ks & 1) * 32, sc);
            }
            wg_commit();
        }
        wg_wait<1>();
        if (it > 0 && !hold) release(it - 1);
    }
    if (wg == 0 && lane == 0) mbar_arrive(BAR(go));
    asm volatile("setmaxnreg.inc.sync.aligned.u32 %0;" ::"n"(R_CONS));
    mbar_wait(BAR(prep), 0);
    const uint32_t ob = layer ^ 1;
    const bool first = (blk == 0 && w == 0);
    const bool sel0 = (2 * q > g), sel1 = (2 * q + 1 > g);
    constexpr float SC = 0.22360679774997896f * 1.4426950408889634f;
    const float m0 = __uint_as_float(lds32(MISC(mean) + 4 * (16 * warp + g))), m1 = __uint_as_float(lds32(MISC(mean) + 4 * (16 * warp + g + 8)));
    uint4 cs[3][5];
    auto cs_load = [&](int p) {
#pragma unroll
        for (int i = 0; i < 5; i++) cs[p][i] = lds128(MISC(cs) + 4 * (80 * p + 20 * q + 4 * i));
    };
    cs_load(1); cs_load(2);
    wg_wait<0>();
    TS(7);
    if (lane == 0) mbar_arrive(BAR(qdone));
    uint32_t ql[10], qh[10], kl[10], kh[10], vl[10], vh[10];
    auto fold = [&](int p, int f, int h) {
        const int j = (f < 8) ? 8 * p + f : 24 + 2 * p + (f - 8);
        const float c0 = __uint_as_float(u4(cs[p][f >> 1], 2 * (f & 1))), c1 = __uint_as_float(u4(cs[p][f >> 1], 2 * (f & 1) + 1));
        const float m = h ? m1 : m0;
        return pack2(fmaf(-m, c0, acc[4 * j + 2 * h]), fmaf(-m, c1, acc[4 * j + 2 * h + 1]));
    };
#pragma unroll
    for (int f = 0; f < 10; f++) { vh[f] = fold(2, f, 1); if (f < A_VLO) vl[f] = fold(2, f, 0); }
#pragma unroll
    for (int f = 0; f < 10; f++) kh[f] = fold(1, f, 1);
#pragma unroll
    for (int f = 0; f < A_VLO; f++) asm volatile("" : "+r"(vl[f]));
    {
        const uint32_t mk = w == 3 ? 1u : 0u;
        auto mark = [&](uint32_t& v) { v = (v & ~mk) | (ob & mk); };
        mark(kh[0]); mark(kh[5]); mark(vh[0]); mark(vh[4]); mark(vh[8]);
    }
    if (w == 3) {
        uint4* hp = &g_halo[bx][wg][0][lane];
        st_ll4(hp, kh[0], kh[1], kh[3], kh[4]); st_ll4(hp + 32, kh[5], kh[6], kh[8], kh[9]);
        st_ll4(hp + 64, vh[0], vh[1], vh[2], vh[3]); st_ll4(hp + 96, vh[4], vh[5], vh[6], vh[7]);
        st_ll4(hp + 128, vh[8], vh[9], kh[2], kh[7]);
    } else {
        const uint32_t a = sb + Q_EOFF + wg * 8192 + w * Q_ESLOT + mj * Q_EROW + mi * 16;
        stsm_x4(a, kh[0], kh[1], kh[3], kh[4]);
        stsm_x4(a + 64, kh[5], kh[6], kh[8], kh[9]);
        stsm_x4(a + 128, vh[0], vh[1], vh[2], vh[3]);
        stsm_x4(a + 192, vh[4], vh[5], vh[6], vh[7]);
        stsm_x4(a + 256, vh[8], vh[9], kh[2], kh[7]);
        __syncwarp();
        if (lane == 0) mbar_arrive(BAR(ex) + 8 * warp);
    }
    TS(9);
    cs_load(0);
#pragma unroll
    for (int f = 0; f < 10; f++) { kl[f] = fold(1, f, 0); if (f >= A_VLO) vl[f] = fold(2, f, 0); }
#pragma unroll
    for (int f = 0; f < 10; f++) { ql[f] = fold(0, f, 0); qh[f] = fold(0, f, 1); }
    auto rs = [&](int i) { return __uint_as_float(lds32(MISC(rstd) + 4 * (72 * wg + 16 * w + i))); };
    const float kx0 = rs(2 * q + (sel0 ? 0 : 8)), kx1 = rs(2 * q + (sel1 ? 1 : 9)), ky0 = rs(2 * q + (sel0 ? 8 : 16)), ky1 = rs(2 * q + (sel1 ? 9 : 17));
    const float rx = SC * rs(8 + g), ry = SC * rs(16 + g), cx0 = rx * kx0, cx1 = rx * kx1, cy0 = ry * ky0, cy1 = ry * ky1;
    uint4 hv[5];
    const uint4* hp = &g_halo[bx - 1][wg][0][lane];
    auto prev = [&] {
        if (w > 0) {
            const uint32_t a = sb + Q_EOFF + wg * 8192 + (w - 1) * Q_ESLOT + mj * Q_EROW + mi * 16;
            mbar_wait(BAR(ex) + 8 * (warp - 1), 0);
            ldsm_x4(hv[0].x, hv[0].y, hv[0].z, hv[0].w, a);
            ldsm_x4(hv[1].x, hv[1].y, hv[1].z, hv[1].w, a + 64);
            ldsm_x4_t(hv[2].x, hv[2].y, hv[2].z, hv[2].w, a + 128);
            ldsm_x4_t(hv[3].x, hv[3].y, hv[3].z, hv[3].w, a + 192);
            ldsm_x2_t(hv[4].x, hv[4].y, a + 256);
            ldsm_x2(hv[4].z, hv[4].w, a + 288 - (lane >> 4) * 32);
        } else if (blk > 0) {
#pragma unroll
            for (int f = 0; f < 5; f++) hv[f] = ld_ll4(hp + 32 * f);
        } else {
#pragma unroll
            for (int f = 0; f < 5; f++) hv[f] = make_uint4(0, 0, 0, 0);
        }
    };
    uint32_t vt[10][2];
#pragma unroll
    for (int f = 0; f < 10; f++) { vt[f][0] = movm_t(vl[f]); vt[f][1] = movm_t(vh[f]); }
    prev();
    TS(10);
    auto FA = [](int h) { return h == 0 ? 0 : h == 1 ? 3 : h == 2 ? 5 : 8; };
    auto FH = [](int h) { return h < 2 ? 2 : 7; };
    const uint32_t pm = (sel0 ? 0xFFFFu : 0u) | (sel1 ? 0xFFFF0000u : 0u);
    auto softmax = [&](float x0, float x1, float k0, float k1) {
        float mx = fmaxf(x0, x1);
        mx = fmaxf(mx, __shfl_xor_sync(~0u, mx, 1));
        mx = fmaxf(mx, __shfl_xor_sync(~0u, mx, 2));
        x0 = ex2(x0 - mx); x1 = ex2(x1 - mx);
        float sx = x0 + x1;
        sx += __shfl_xor_sync(~0u, sx, 1);
        sx += __shfl_xor_sync(~0u, sx, 2);
        const float ix = frcp(sx);
        return pack2(x0 * k0 * ix, x1 * k1 * ix);
    };
    uint32_t qm[4][2], py[4];
    float sl[4][2];
#pragma unroll
    for (int h = 0; h < 4; h++) {
        const int fa = FA(h), fb = fa + 1, fh = FH(h);
        const bool mine = (h & 1) ? (q >= 2) : (q < 2);
        qm[h][0] = mine ? ql[fh] : 0u; qm[h][1] = mine ? qh[fh] : 0u;
        float S1[4] = {0.f, 0.f, 0.f, 0.f}, S2[4] = {0.f, 0.f, 0.f, 0.f};
        mma16816(S1, ql[fa], qh[fa], ql[fb], qh[fb], kl[fa], kl[fb]); mma1688(S1, qm[h][0], qm[h][1], kl[fh]);
        mma16816(S2, ql[fa], qh[fa], ql[fb], qh[fb], kh[fa], kh[fb]); mma1688(S2, qm[h][0], qm[h][1], kh[fh]);
        sl[h][0] = S1[0]; sl[h][1] = S1[1];
        py[h] = softmax((sel0 ? S1[2] : S2[2]) * cy0, (sel1 ? S1[3] : S2[3]) * cy1, ky0, ky1);
    }
    TS(11);
    if (w == 0 && blk > 0) {
        ll_check5(hv, hp, ob);
#pragma unroll
        for (int f = 2; f < 4; f++) hv[f] = make_uint4(movm_t(hv[f].x), movm_t(hv[f].y), movm_t(hv[f].z), movm_t(hv[f].w));
        hv[4].x = movm_t(hv[4].x); hv[4].y = movm_t(hv[4].y);
    }
    const uint32_t kp[10] = {hv[0].x, hv[0].y, hv[4].z, hv[0].z, hv[0].w, hv[1].x, hv[1].y, hv[4].w, hv[1].z, hv[1].w};
    const uint32_t vp[10] = {hv[2].x, hv[2].y, hv[2].z, hv[2].w, hv[3].x, hv[3].y, hv[3].z, hv[3].w, hv[4].x, hv[4].y};
    TS(12);
    const uint4 ko[2] = {ldg_tab(16, tid & 127), ldg_tab(17, tid & 127)};
    const float bx0 = first && sel0 ? -INFINITY : 0.f, bx1 = first && sel1 ? -INFINITY : 0.f;
    float oacc[10][4];
#pragma unroll
    for (int h = 0; h < 4; h++) {
        const int fa = FA(h), fb = fa + 1, fh = FH(h);
        const bool mine = (h & 1) ? (q >= 2) : (q < 2);
        float S0[4] = {0.f, 0.f, 0.f, 0.f};
        mma16816(S0, ql[fa], qh[fa], ql[fb], qh[fb], kp[fa], kp[fb]); mma1688(S0, qm[h][0], qm[h][1], kp[fh]);
        const uint32_t px = softmax(fmaf(sel0 ? S0[0] : sl[h][0], cx0, bx0), fmaf(sel1 ? S0[1] : sl[h][1], cx1, bx1), kx0, kx1);
#pragma unroll
        for (int i = 0; i < 3; i++) {
            const int f = (i == 0) ? fa : (i == 1) ? fb : fh;
            float O[4] = {0.f, 0.f, 0.f, 0.f};
            mma16816(O, px & ~pm, py[h] & pm, 0u, py[h] & ~pm, vt[f][0], vt[f][1]);
            mma1688(O, px & pm, 0u, vp[f]);
            if (i < 2 || !(h & 1) || mine) { oacc[f][0] = O[0]; oacc[f][1] = O[1]; oacc[f][2] = O[2]; oacc[f][3] = O[3]; }
        }
    }
    TS(13);
    float aw[40];
    uint4 of[5];
    {
        const uint32_t fb = EPOCH ^ ob, mk[2] = {q == ((2 * w) & 3), q == ((2 * w + 1) & 3)};
        uint32_t* dst = &g_of[hg][blk][640 * wg + 16 * w].x + lane;
#pragma unroll
        for (int i = 0; i < 20; i++) {
            const uint32_t v = (pack2(oacc[i >> 1][2 * (i & 1)], oacc[i >> 1][2 * (i & 1) + 1]) & ~mk[i & 1]) | (fb & mk[i & 1]);
            u4r(of[i >> 2], i & 3) = v;
            asm volatile("st.relaxed.gpu.global.u32 [%0], %1;" ::"l"(dst + 256 * (i >> 1) + 32 * (i & 1)), "r"(v) : "memory");
        }
        if (lane == 0) mbar_arrive(BAR(att) + 8 * wg);
        TS(14);
    }
    const uint32_t obar = MISC(ob) + 32 * wg;
    named_bar(1 + wg, 128);
    kernel_stage<2>(ko, sb + Q_KDUMP + 2 * wg * KG_RES, MISC(kg), 2 * wg, sb + F_EO + wg * 8192, w, lane);
    TS(15);
    uint32_t res[20];
    mbar_wait(BAR(res), 0);
    const uint32_t ta = (8 * (mi >> 1) + mj) * 128 + (((2 * w + (mi & 1)) ^ mj) << 4);
    if (layer == 0) {
        const int tok = 16 * w + 8 * (mi & 1) + mj;
#pragma unroll
        for (int k = 0; k < 4; k++)
            ldsm_x4(res[4 * k], res[4 * k + 1], res[4 * k + 2], res[4 * k + 3], sb + W_RES + wg * 10240 + tok * 128 + (((2 * k + (mi >> 1)) ^ mj) << 4));
        ldsm_x4(res[16], res[17], res[18], res[19], sb + W_RES + wg * 10240 + 8192 + tok * 32 + (((mi >> 1) ^ (mj >> 2)) << 4));
    } else {
#pragma unroll
        for (int k = 0; k < 5; k++) ldsm_x4_t(res[4 * k], res[4 * k + 1], res[4 * k + 2], res[4 * k + 3], sb + W_RES + wg * 10240 + k * 2048 + ta);
    }
    fence_async_smem();
    __syncwarp();
    if (lane == 0) mbar_arrive(obar + 128 + 24);
    {
#pragma unroll
        for (int i = 0; i < 20; i++) { aw[2 * i] = bf_lo(res[i]); aw[2 * i + 1] = bf_hi(res[i]); }
        mbar_wait(BAR(wfull), 0);
        const uint64_t dm = mkdesc(sb + w_grp(0), 1280, 128, 0);
        wg_fence();
#pragma unroll
        for (int k = 0; k < 5; k++) wgmma_rs80(aw, of[k], dm + k * 160, 1);
        wg_commit();
    }
    conv_tables();
    wg_wait<0>();
    TS(8);
#pragma unroll 1
    for (int j = 1; j < 8; j++) {
        const int s = (j - 1) & 3;
        const uint64_t da = mkdesc(sb + o_slot(wg, s), 1024, 128, 0), dm = mkdesc(sb + w_grp(j), 1280, 128, 0);
        if (s == 2) mbar_wait(BAR(wfull) + 2 * (j + 1), 0);
        mbar_wait(obar + 64 + 8 * s, s == 3 ? layer : j > 4);
        if (j == 1) TS(17);
        if (j == 5) TS(18);
        wg_fence();
#pragma unroll
        for (int k = 0; k < 5; k++) wgmma_ss80(aw, da + k * 128, dm + k * 160);
        wg_commit();
        wg_wait<1>();
        if (j > 1 && j < 5 && lane == 0) mbar_arrive(obar + 128 + 8 * (j - 2));
    }
    if (lane == 0) mbar_arrive(BAR(soon) + 8 * wg);
    named_bar(1 + wg, 128);
    wg_wait<0>();
    TS(19);
    {
        float a[2][4] = {{0.f, 0.f, 0.f, 0.f}, {0.f, 0.f, 0.f, 0.f}};
#pragma unroll
        for (int i = 0; i < 40; i++) { a[i & 1][i & 2] += aw[i]; a[i & 1][(i & 2) + 1] = fmaf(aw[i], aw[i], a[i & 1][(i & 2) + 1]); }
#pragma unroll
        for (int j = 0; j < 4; j++) { a[0][j] += a[1][j]; a[0][j] += __shfl_xor_sync(~0u, a[0][j], 1); a[0][j] += __shfl_xor_sync(~0u, a[0][j], 2); }
        if (q == 0) st_ll4(&g_sp2[blk][warp][hg][g], (__float_as_uint(a[0][0]) & ~1u) | ob, __float_as_uint(a[0][1]), __float_as_uint(a[0][2]), __float_as_uint(a[0][3]));
    }
    TS(23);
#pragma unroll
    for (int i = 0; i < 20; i++) res[i] = pack2(aw[2 * i], aw[2 * i + 1]);
    {
        const uint32_t mk = (g & 3) ? 0u : 0x00010001u;
#pragma unroll
        for (int k = 0; k < 5; k++) {
            uint32_t m[4];
#pragma unroll
            for (int i = 0; i < 4; i++) m[i] = (res[4 * k + i] & ~mk) | (mk & (0u - ob));
            stsm_x4_t(sb + w_out(wg) + k * 2048 + ta, m[0], m[1], m[2], m[3]);
        }
        fence_async_smem();
        named_bar(1 + wg, 128);
        if (w == 0 && elect_one()) {
            asm volatile("cp.async.bulk.tensor.2d.global.shared::cta.bulk_group [%0, {%2, %3}], [%1];"
                         ::"l"(TMAP(7)), "r"(sb + w_out(wg)), "r"(1024 * wg + 64 * blk), "r"(hg * 80) : "memory");
            bulk_commit();
            mbar_arrive(BAR(staged));
        }
        __syncwarp();
        TS(20);
    }
    if (layer) {
#pragma unroll
        for (int k = 0; k < 5; k++) stsm_x4_t(sb + W_RES + wg * 10240 + k * 2048 + ta, res[4 * k], res[4 * k + 1], res[4 * k + 2], res[4 * k + 3]);
    }
    TS(22);
    TS_PHASE(2 * layer + 1);
    TS(0);
    indices();
    conv_wg<2>(cta_channel(bx, 2 * (warp >> 2)), layer, sb + F_EO + (warp >> 2) * 8192, sb + (1 + 2 * (warp >> 2)) * Q_SB, sb + F_S23, MISC(kg.kexp) + 8 * (warp >> 2),
               MISC(epoch), sb, BAR(st), BAR(fdone0), warp, lane, fa1, ftw, [&] {
        if ((warp & 3) == 0 && elect_one()) {
            asm volatile("cp.async.bulk.wait_group.read 0;" ::: "memory");
            if (layer == 0) { mbar_arrive_cta(BAR(wfree), 0); mbar_arrive_cta(BAR(wfree), 1); }
        }
        __syncwarp();
        if (warp < 4) mbar_wait(BAR(staged), 0);
    }, [&] {
        if (layer == 0 && warp >= 4 && elect_one()) {
            mbar_wait(BAR(wfree), 0);
            issue_w(BAR(full) + sizeof(Bars), warp - 4, 1);
        }
        __syncwarp();
    } TS_PASS);
    __syncwarp();
    if (lane == 0) mbar_arrive(warp < 4 ? BAR(fdone0) : BAR(fdone1));
    TS(20);
    asm volatile("setmaxnreg.dec.sync.aligned.u32 168;");
    }
    named_bar(1 + (warp >> 2), 128);
    asm volatile("setmaxnreg.dec.sync.aligned.u32 %0;" ::"n"(504 - 2 * R_CONS));
    }
    indices();
    const int cq = 4 * (warp >> 1) + (lane & 3), tg = 8 * (warp & 1) + (lane >> 2);
    const uint32_t fb = ~EPOCH & 1u;
    uint2 xr[4][2];
    __syncthreads();
    if (tid < 320) {
#pragma unroll
        for (int i = 0; i < 8; i++) {
            const int ch = 4 * cq + (i >> 1);
            asm volatile("ld.shared.v2.u32 {%0, %1}, [%2];" : "=r"(xr[i >> 1][i & 1].x), "=r"(xr[i >> 1][i & 1].y)
                         : "r"(sb + W_RES + (i & 1) * 10240 + ch * 128 + (((tg >> 1) ^ (ch & 7)) << 4) + (tg & 1) * 8) : "memory");
        }
    }
    if (tid < 320) {
        const uint4* src = &g_of[hg][blk][64 * cq + tg];
        uint4 v[4];
#pragma unroll
        for (int i = 0; i < 4; i++) v[i] = make_uint4(~fb, ~fb, ~fb, ~fb);
        auto miss = [&](int i) { return (((warp & 1) ? u4(v[i], 2 * (i & 1) + 1) : u4(v[i], 2 * (i & 1))) ^ fb) & 1u; };
        int spin = 0;
        while (true) {
#pragma unroll
            for (int i = 0; i < 4; i++) if (miss(i)) v[i] = ld_ll4(src + 16 * i);
            if (!(miss(0) | miss(1) | miss(2) | miss(3)) || ++spin >= (1 << 18)) break;
        }
        TS(21);
#pragma unroll
        for (int i = 0; i < 16; i++) asm("add.rn.bf16x2 %0, %0, %1;" : "+r"(u4r(v[i >> 2], i & 3)) : "r"((i & 1) ? xr[i >> 2][(i >> 1) & 1].y : xr[i >> 2][(i >> 1) & 1].x));
#pragma unroll
        for (int j = 0; j < 8; j++) {
            const uint32_t sel = (j & 2) ? 0x7632 : 0x5410;
            const int k = 2 * (j & 1) + (j >> 2);
            asm volatile("st.shared.v2.u32 [%0], {%1, %2};" ::"r"(sb + 2 * Q_SB + (16 * j + tg) * 160 + cq * 8),
                         "r"(__byte_perm(u4(v[0], k), u4(v[1], k), sel)), "r"(__byte_perm(u4(v[2], k), u4(v[3], k), sel)) : "memory");
        }
        fence_async_smem();
    }
    __syncthreads();
    if (warp == 0 && elect_one()) {
        asm volatile("cp.async.bulk.tensor.3d.global.shared::cta.bulk_group [%0, {%2, %3, 0}], [%1];" ::"l"(TMAP(9)), "r"(sb + 2 * Q_SB), "r"(80 * hg), "r"(16 * blk) : "memory");
        bulk_commit();
        asm volatile("cp.async.bulk.wait_group.read 0;" ::: "memory");
    }
    if (bx == 0 && tid == 0) g_epoch = (EPOCH + 1) & 0x3FFFFFFFu;
    TS(22);
    TS_END;
}
typedef CUresult (*EncodeTiledFn)(CUtensorMap*, CUtensorMapDataType, cuuint32_t, void*, const cuuint64_t*, const cuuint64_t*, const cuuint32_t*,
                                  const cuuint32_t*, CUtensorMapInterleave, CUtensorMapSwizzle, CUtensorMapL2promotion, CUtensorMapFloatOOBfill);

static void make_map(EncodeTiledFn enc, CUtensorMap* m, const void* base, int rank, const cuuint64_t* dims, const cuuint64_t* strides,
                     const cuuint32_t* box, CUtensorMapSwizzle sw) {
    cuuint32_t es[4] = {1, 1, 1, 1};
    enc(m, CU_TENSOR_MAP_DATA_TYPE_BFLOAT16, rank, (void*)base, dims, strides, box, es, CU_TENSOR_MAP_INTERLEAVE_NONE, sw,
        sw == CU_TENSOR_MAP_SWIZZLE_128B ? CU_TENSOR_MAP_L2_PROMOTION_L2_128B : CU_TENSOR_MAP_L2_PROMOTION_NONE, CU_TENSOR_MAP_FLOAT_OOB_FILL_NONE);
}

template <typename... KArgs, typename... Args>
static void launch(void (*kern)(KArgs...), int grid, int block, int smem, int cluster, bool pdl, Args... args) {
    cudaLaunchConfig_t cfg = {};
    cfg.gridDim = dim3(grid); cfg.blockDim = dim3(block); cfg.dynamicSmemBytes = smem; cfg.stream = cudaStreamPerThread;
    cudaLaunchAttribute at[2];
    int n = 0;
    if (cluster > 1) { at[n].id = cudaLaunchAttributeClusterDimension; at[n].val.clusterDim.x = cluster; at[n].val.clusterDim.y = 1; at[n].val.clusterDim.z = 1; n++; }
    if (pdl) { at[n].id = cudaLaunchAttributeProgrammaticStreamSerialization; at[n].val.programmaticStreamSerializationAllowed = 1; n++; }
    cfg.attrs = at; cfg.numAttrs = n;
    cudaLaunchKernelEx(&cfg, kern, KArgs(args)...);
}

struct HostState {
    bool ready = false;
    const void* key[4] = {nullptr, nullptr, nullptr, nullptr};
    CUtensorMap mX[2], mRes[2], mW, mWr, mWo, mOut, mFin, mResA;
    bf16 *x1T, *x2T;
    unsigned* epoch;
};

extern "C" void kernel_launch(void* const* d_in, const int* in_sizes, int n_in, void* d_out, int out_size) {
    const bf16* x = (const bf16*)d_in[0];
    const bf16* wqkv = (const bf16*)d_in[1];
    const bf16* wo = (const bf16*)d_in[2];
    const bf16* lar = (const bf16*)d_in[4];
    const bf16* aim = (const bf16*)d_in[5];
    const bf16* cre = (const bf16*)d_in[6];
    const bf16* cim = (const bf16*)d_in[7];
    const bf16* logdt = (const bf16*)d_in[8];
    const bf16* dskip = (const bf16*)d_in[9];
    static HostState hs;
    if (!hs.ready || hs.key[0] != wqkv || hs.key[1] != wo || hs.key[2] != x || hs.key[3] != d_out) {
        void* fn = nullptr;
        cudaDriverEntryPointQueryResult qr;
        cudaGetDriverEntryPoint("cuTensorMapEncodeTiled", &fn, cudaEnableDefault, &qr);
        EncodeTiledFn enc = (EncodeTiledFn)fn;
        cudaGetSymbolAddress((void**)&hs.epoch, g_epoch);
        cudaGetSymbolAddress((void**)&hs.x1T, g_x1T);
        cudaGetSymbolAddress((void**)&hs.x2T, g_x2T);
        {
            cuuint64_t d[3] = {DM, SEQ / 2, 2}, s[2] = {DM * 4, DM * 2};
            cuuint32_t b[3] = {64, 64, 2}, ba[3] = {64, 64, 1}, br[3] = {16, 64, 1};
            make_map(enc, &hs.mX[0], x, 3, d, s, b, CU_TENSOR_MAP_SWIZZLE_128B);
            make_map(enc, &hs.mResA, x, 3, d, s, ba, CU_TENSOR_MAP_SWIZZLE_128B);
            make_map(enc, &hs.mRes[0], x, 3, d, s, br, CU_TENSOR_MAP_SWIZZLE_32B);
            cuuint64_t d2[3] = {SEQ / 2, DM, 2}, s2[2] = {XP * 2, SEQ};
            cuuint32_t b2[3] = {64, 80, 2};
            make_map(enc, &hs.mX[1], hs.x2T, 3, d2, s2, b, CU_TENSOR_MAP_SWIZZLE_128B);
            make_map(enc, &hs.mRes[1], hs.x2T, 3, d2, s2, b2, CU_TENSOR_MAP_SWIZZLE_128B);
            cuuint64_t d3[2] = {SEQ, DM};
            make_map(enc, &hs.mOut, hs.x1T, 2, d3, s2, b2, CU_TENSOR_MAP_SWIZZLE_128B);
        }
        { cuuint64_t d[2] = {3 * DM, DM}, s[1] = {3 * DM * 2}; cuuint32_t b[2] = {64, 32};
          make_map(enc, &hs.mW, wqkv, 2, d, s, b, CU_TENSOR_MAP_SWIZZLE_128B); }
        { cuuint64_t d[3] = {DM, DM, 3}, s[2] = {3 * DM * 2, DM * 2}; cuuint32_t b[3] = {16, 32, 3};
          make_map(enc, &hs.mWr, wqkv, 3, d, s, b, CU_TENSOR_MAP_SWIZZLE_32B); }
        { cuuint64_t d[4] = {8, 8, DM / 8, DM / 8}, s[3] = {DM * 2, 16, DM * 16}; cuuint32_t b[4] = {8, 8, 10, 5};
          make_map(enc, &hs.mWo, wo, 4, d, s, b, CU_TENSOR_MAP_SWIZZLE_NONE); }
        { cuuint64_t d[3] = {DM, SEQ / 8, 8}, s[2] = {DM * 16, DM * 2}; cuuint32_t b[3] = {80, 16, 8};
          make_map(enc, &hs.mFin, d_out, 3, d, s, b, CU_TENSOR_MAP_SWIZZLE_NONE); }
        cudaFuncSetAttribute(fused_kernel, cudaFuncAttributeMaxDynamicSharedMemorySize, Q_SMEM);
        hs.key[0] = wqkv; hs.key[1] = wo; hs.key[2] = x; hs.key[3] = d_out;
        hs.ready = true;
    }
    const SsmParams sp = {lar, aim, cre, cim, logdt, dskip, hs.epoch};
    launch(fused_kernel, 128, 384, Q_SMEM, 2, false, sp, hs.mX[0], hs.mX[1], hs.mW, hs.mWr, hs.mRes[0], hs.mRes[1], hs.mOut, hs.mWo, hs.mFin, hs.mResA);
}
```

```cpp
#include <cuda_runtime.h>
#include <cuda.h>
#include <cuda_bf16.h>
#include <cuda_fp16.h>
#include <stdint.h>

typedef __nv_bfloat16 bf16;

constexpr int SEQ = 2048;
constexpr int DM  = 640;
constexpr int XP  = SEQ + 64;
constexpr int NMODE = 192;
#define HINT_SPINS (1 << 18)

__device__ __forceinline__ uint32_t s2u(const void* p) { return (uint32_t)__cvta_generic_to_shared(p); }
__device__ __forceinline__ void mbar_init(uint32_t b, int c) { asm volatile("mbarrier.init.shared::cta.b64 [%0], %1;" ::"r"(b), "r"(c)); }
__device__ __forceinline__ void mbar_expect(uint32_t b, uint32_t bytes) { asm volatile("mbarrier.arrive.expect_tx.shared::cta.b64 _, [%0], %1;" ::"r"(b), "r"(bytes) : "memory"); }
__device__ __forceinline__ void mbar_arrive(uint32_t b) { asm volatile("mbarrier.arrive.shared::cta.b64 _, [%0];" ::"r"(b) : "memory"); }
__device__ __forceinline__ void mbar_arrive_cta(uint32_t b, uint32_t cta) {
    asm volatile("{\n.reg .b32 ra;\nmapa.shared::cluster.u32 ra, %0, %1;\nmbarrier.arrive.shared::cluster.b64 _, [ra];\n}" ::"r"(b), "r"(cta) : "memory");
}
__device__ __forceinline__ void mbar_wait(uint32_t b, uint32_t ph) {
#ifdef M_SAFE
    asm volatile("{\n.reg .pred p;\n.reg .u32 n;\nmbarrier.try_wait.parity.shared::cta.b64 p, [%0], %1;\n@p bra D;\nmov.u32 n, 0;\n"
                 "W: mbarrier.try_wait.parity.shared::cta.b64 p, [%0], %1;\n@p bra D;\nadd.u32 n, n, 1;\nsetp.lt.u32 p, n, 4194304;\n@p bra W;\ntrap;\nD:\n}"
                 ::"r"(b), "r"(ph) : "memory");
#else
    asm volatile("{\n.reg .pred p;\nW: mbarrier.try_wait.parity.shared::cta.b64 p, [%0], %1;\n@!p bra W;\n}" ::"r"(b), "r"(ph) : "memory");
#endif
}
__device__ __forceinline__ void fence_mbar_init() { asm volatile("fence.mbarrier_init.release.cluster;" ::: "memory"); }
__device__ __forceinline__ void cluster_sync() { asm volatile("barrier.cluster.arrive.aligned;\nbarrier.cluster.wait.aligned;" ::: "memory"); }
__device__ __forceinline__ void pdl_wait() { asm volatile("griddepcontrol.wait;" ::: "memory"); }
__device__ __forceinline__ void pdl_launch() { asm volatile("griddepcontrol.launch_dependents;" ::: "memory"); }
__device__ __forceinline__ void named_bar(int id, int n) { asm volatile("bar.sync %0, %1;" ::"r"(id), "r"(n) : "memory"); }
__device__ __forceinline__ void fence_async_smem() { asm volatile("fence.proxy.async.shared::cta;" ::: "memory"); }

__device__ __forceinline__ void tma2d(uint32_t dst, const CUtensorMap* m, int c0, int c1, uint32_t bar) {
    asm volatile("cp.async.bulk.tensor.2d.shared::cluster.global.mbarrier::complete_tx::bytes [%0], [%1, {%3, %4}], [%2];"
                 ::"r"(dst), "l"(m), "r"(bar), "r"(c0), "r"(c1) : "memory");
}
__device__ __forceinline__ void tma2d_mc(uint32_t dst, const CUtensorMap* m, int c0, int c1, uint32_t bar, uint16_t mask) {
    asm volatile("cp.async.bulk.tensor.2d.shared::cluster.global.mbarrier::complete_tx::bytes.multicast::cluster [%0], [%1, {%3, %4}], [%2], %5;"
                 ::"r"(dst), "l"(m), "r"(bar), "r"(c0), "r"(c1), "h"(mask) : "memory");
}
__device__ __forceinline__ void tma3d(uint32_t dst, const CUtensorMap* m, int c0, int c1, int c2, uint32_t bar) {
    asm volatile("cp.async.bulk.tensor.3d.shared::cluster.global.mbarrier::complete_tx::bytes [%0], [%1, {%3, %4, %5}], [%2];"
                 ::"r"(dst), "l"(m), "r"(bar), "r"(c0), "r"(c1), "r"(c2) : "memory");
}
__device__ __forceinline__ void tma3d_mc(uint32_t dst, const CUtensorMap* m, int c0, int c1, int c2, uint32_t bar, uint16_t mask) {
    asm volatile("cp.async.bulk.tensor.3d.shared::cluster.global.mbarrier::complete_tx::bytes.multicast::cluster [%0], [%1, {%3, %4, %5}], [%2], %6;"
                 ::"r"(dst), "l"(m), "r"(bar), "r"(c0), "r"(c1), "r"(c2), "h"(mask) : "memory");
}
__device__ __forceinline__ void bulk_g2s(uint32_t dst, const void* src, uint32_t bytes, uint32_t bar) {
    asm volatile("cp.async.bulk.shared::cluster.global.mbarrier::complete_tx::bytes [%0], [%1], %2, [%3];"
                 ::"r"(dst), "l"(src), "r"(bytes), "r"(bar) : "memory");
}
__device__ __forceinline__ void bulk_g2s_mc(uint32_t dst, const void* src, uint32_t bytes, uint32_t bar, uint16_t mask) {
    asm volatile("cp.async.bulk.shared::cluster.global.mbarrier::complete_tx::bytes.multicast::cluster [%0], [%1], %2, [%3], %4;"
                 ::"r"(dst), "l"(src), "r"(bytes), "r"(bar), "h"(mask) : "memory");
}
__device__ __forceinline__ void prefetch_l2(const void* p, uint32_t bytes) { asm volatile("cp.async.bulk.prefetch.L2.global [%0], %1;" ::"l"(p), "r"(bytes) : "memory"); }
__device__ __forceinline__ void prefetch_tmap(const CUtensorMap* m) { asm volatile("prefetch.tensormap [%0];" ::"l"(m) : "memory"); }

__device__ __forceinline__ void wg_fence() { asm volatile("wgmma.fence.sync.aligned;" ::: "memory"); }
__device__ __forceinline__ void wg_commit() { asm volatile("wgmma.commit_group.sync.aligned;" ::: "memory"); }
template <int N> __device__ __forceinline__ void wg_wait() { asm volatile("wgmma.wait_group.sync.aligned %0;" ::"n"(N) : "memory"); }
__device__ __forceinline__ uint64_t mkdesc(uint32_t addr, uint32_t lbo, uint32_t sbo, uint32_t mode) {
    return (uint64_t)((addr & 0x3FFFF) >> 4) | ((uint64_t)(lbo >> 4) << 16) | ((uint64_t)(sbo >> 4) << 32) | ((uint64_t)mode << 62);
}

__device__ __forceinline__ void mma16816(float (&c)[4], uint32_t a0, uint32_t a1, uint32_t a2, uint32_t a3, uint32_t b0, uint32_t b1) {
    asm("mma.sync.aligned.m16n8k16.row.col.f32.bf16.bf16.f32 {%0,%1,%2,%3},{%4,%5,%6,%7},{%8,%9},{%0,%1,%2,%3};"
                 : "+f"(c[0]), "+f"(c[1]), "+f"(c[2]), "+f"(c[3]) : "r"(a0), "r"(a1), "r"(a2), "r"(a3), "r"(b0), "r"(b1));
}
__device__ __forceinline__ void mma1688(float (&c)[4], uint32_t a0, uint32_t a1, uint32_t b0) {
    asm("mma.sync.aligned.m16n8k8.row.col.f32.bf16.bf16.f32 {%0,%1,%2,%3},{%4,%5},{%6},{%0,%1,%2,%3};"
                 : "+f"(c[0]), "+f"(c[1]), "+f"(c[2]), "+f"(c[3]) : "r"(a0), "r"(a1), "r"(b0));
}
__device__ __forceinline__ void ldsm_x4(uint32_t& r0, uint32_t& r1, uint32_t& r2, uint32_t& r3, uint32_t a) {
    asm volatile("ldmatrix.sync.aligned.m8n8.x4.shared.b16 {%0,%1,%2,%3}, [%4];" : "=r"(r0), "=r"(r1), "=r"(r2), "=r"(r3) : "r"(a) : "memory");
}
__device__ __forceinline__ void ldsm_x4_t(uint32_t& r0, uint32_t& r1, uint32_t& r2, uint32_t& r3, uint32_t a) {
    asm volatile("ldmatrix.sync.aligned.m8n8.x4.trans.shared.b16 {%0,%1,%2,%3}, [%4];" : "=r"(r0), "=r"(r1), "=r"(r2), "=r"(r3) : "r"(a) : "memory");
}
__device__ __forceinline__ void ldsm_x2(uint32_t& r0, uint32_t& r1, uint32_t a) {
    asm volatile("ldmatrix.sync.aligned.m8n8.x2.shared.b16 {%0,%1}, [%2];" : "=r"(r0), "=r"(r1) : "r"(a) : "memory");
}
__device__ __forceinline__ void ldsm_x2_t(uint32_t& r0, uint32_t& r1, uint32_t a) {
    asm volatile("ldmatrix.sync.aligned.m8n8.x2.trans.shared.b16 {%0,%1}, [%2];" : "=r"(r0), "=r"(r1) : "r"(a) : "memory");
}
__device__ __forceinline__ void stsm_x4(uint32_t a, uint32_t r0, uint32_t r1, uint32_t r2, uint32_t r3) {
    asm volatile("stmatrix.sync.aligned.m8n8.x4.shared.b16 [%0], {%1,%2,%3,%4};" ::"r"(a), "r"(r0), "r"(r1), "r"(r2), "r"(r3) : "memory");
}
__device__ __forceinline__ void stsm_x4_t(uint32_t a, uint32_t r0, uint32_t r1, uint32_t r2, uint32_t r3) {
    asm volatile("stmatrix.sync.aligned.m8n8.x4.trans.shared.b16 [%0], {%1,%2,%3,%4};" ::"r"(a), "r"(r0), "r"(r1), "r"(r2), "r"(r3) : "memory");
}
__device__ __forceinline__ void stsm_x2(uint32_t a, uint32_t r0, uint32_t r1) {
    asm volatile("stmatrix.sync.aligned.m8n8.x2.shared.b16 [%0], {%1,%2};" ::"r"(a), "r"(r0), "r"(r1) : "memory");
}
__device__ __forceinline__ uint32_t movm_t(uint32_t a) {
    uint32_t d;
    asm volatile("movmatrix.sync.aligned.m8n8.trans.b16 %0, %1;" : "=r"(d) : "r"(a));
    return d;
}
__device__ __forceinline__ uint32_t lds32(uint32_t a) { uint32_t v; asm volatile("ld.shared.u32 %0, [%1];" : "=r"(v) : "r"(a) : "memory"); return v; }
__device__ __forceinline__ uint32_t ldsv32(uint32_t a) { uint32_t v; asm volatile("ld.volatile.shared.u32 %0, [%1];" : "=r"(v) : "r"(a) : "memory"); return v; }
__device__ __forceinline__ void sts32(uint32_t a, uint32_t v) { asm volatile("st.shared.u32 [%0], %1;" ::"r"(a), "r"(v) : "memory"); }
__device__ __forceinline__ uint4 lds128(uint32_t a) { uint4 v; asm volatile("ld.shared.v4.u32 {%0,%1,%2,%3}, [%4];" : "=r"(v.x), "=r"(v.y), "=r"(v.z), "=r"(v.w) : "r"(a) : "memory"); return v; }
__device__ __forceinline__ void sts128(uint32_t a, uint4 v) { asm volatile("st.shared.v4.u32 [%0], {%1,%2,%3,%4};" ::"r"(a), "r"(v.x), "r"(v.y), "r"(v.z), "r"(v.w) : "memory"); }

__device__ __forceinline__ void stg128(void* p, uint4 v) { asm volatile("st.global.v4.u32 [%0], {%1,%2,%3,%4};" ::"l"(p), "r"(v.x), "r"(v.y), "r"(v.z), "r"(v.w) : "memory"); }

__device__ __forceinline__ uint4 ldg128(const void* p) { uint4 v; asm volatile("ld.global.v4.u32 {%0,%1,%2,%3}, [%4];" : "=r"(v.x), "=r"(v.y), "=r"(v.z), "=r"(v.w) : "l"(p) : "memory"); return v; }
__device__ __forceinline__ uint2 ldg64(const void* p) { uint2 v; asm volatile("ld.global.v2.u32 {%0,%1}, [%2];" : "=r"(v.x), "=r"(v.y) : "l"(p) : "memory"); return v; }
__device__ __forceinline__ uint32_t ldg32(const void* p) { uint32_t v; asm volatile("ld.global.u32 %0, [%1];" : "=r"(v) : "l"(p) : "memory"); return v; }

__device__ __forceinline__ uint32_t pack2(float lo, float hi) {
    uint32_t r;
    asm("cvt.rn.bf16x2.f32 %0, %1, %2;" : "=r"(r) : "f"(hi), "f"(lo));
    return r;
}
__device__ __forceinline__ float bf_lo(uint32_t v) { return __uint_as_float(v << 16); }
__device__ __forceinline__ float bf_hi(uint32_t v) { return __uint_as_float(v & 0xFFFF0000u); }
__device__ __forceinline__ float rbf(float x) { return __uint_as_float(pack2(0.f, x) & 0xFFFF0000u); }
__device__ __forceinline__ float ex2(float x) { float r; asm("ex2.approx.ftz.f32 %0, %1;" : "=f"(r) : "f"(x)); return r; }

__device__ __forceinline__ float2 ln_finish(float sum, float sumsq) {
    const float m = sum * (1.0f / DM);
    const float v = fmaxf(fmaf(sumsq, 1.0f / DM, -m * m), 0.f);
    float s, r;
    asm("sqrt.approx.ftz.f32 %0, %1;" : "=f"(s) : "f"(rbf(rbf(v) + 1e-5f)));
    asm("rcp.approx.ftz.f32 %0, %1;" : "=f"(r) : "f"(rbf(s)));
    return make_float2(m, r);
}
__device__ __forceinline__ uint32_t ln_finish_packed(float sum, float sumsq) {
    const float m = sum * (1.0f / DM);
    const float v = fmaxf(fmaf(sumsq, 1.0f / DM, -m * m), 0.f);
    float s;
    asm("sqrt.approx.ftz.f32 %0, %1;" : "=f"(s) : "f"(rbf(rbf(v) + 1e-5f)));
    return pack2(s, m);
}
__device__ __forceinline__ float frsq(float x) { float r; asm("rsqrt.approx.ftz.f32 %0, %1;" : "=f"(r) : "f"(x)); return r; }
__device__ __forceinline__ float frcp(float x) { float r; asm("rcp.approx.ftz.f32 %0, %1;" : "=f"(r) : "f"(x)); return r; }
__device__ __forceinline__ bool elect_one() {
    uint32_t p;
    asm volatile("{\n.reg .pred p;\nelect.sync _|p, 0xffffffff;\nselp.u32 %0, 1, 0, p;\n}" : "=r"(p));
    return p != 0;
}
__device__ __forceinline__ void cluster_arrive_relaxed() { asm volatile("barrier.cluster.arrive.relaxed.aligned;" ::: "memory"); }
__device__ __forceinline__ void cluster_wait() { asm volatile("barrier.cluster.wait.aligned;" ::: "memory"); }
__device__ __forceinline__ unsigned long long ld_ll(const unsigned long long* p) {
    unsigned long long v;
    asm volatile("ld.relaxed.gpu.global.b64 %0, [%1];" : "=l"(v) : "l"(p) : "memory");
    return v;
}
__device__ __forceinline__ void st_ll(unsigned long long* p, uint32_t payload, uint32_t tag) {
    const unsigned long long v = (unsigned long long)payload | ((unsigned long long)tag << 32);
    asm volatile("st.relaxed.gpu.global.b64 [%0], %1;" ::"l"(p), "l"(v) : "memory");
}
__device__ __forceinline__ uint4 ld_ll4(const uint4* p) {
    uint4 v;
    asm volatile("{\n.reg .b128 t;\n.reg .b64 a, b;\nld.relaxed.gpu.global.b128 t, [%4];\nmov.b128 {a, b}, t;\nmov.b64 {%0, %1}, a;\nmov.b64 {%2, %3}, b;\n}"
                 : "=r"(v.x), "=r"(v.y), "=r"(v.z), "=r"(v.w) : "l"(p) : "memory");
    return v;
}
__device__ __forceinline__ void st_ll4(uint4* p, uint32_t x, uint32_t y, uint32_t z, uint32_t w) {
    asm volatile("{\n.reg .b128 t;\n.reg .b64 a, b;\nmov.b64 a, {%1, %2};\nmov.b64 b, {%3, %4};\nmov.b128 t, {a, b};\nst.relaxed.gpu.global.b128 [%0], t;\n}"
                 ::"l"(p), "r"(x), "r"(y), "r"(z), "r"(w) : "memory");
}

__device__ __forceinline__ void bulk_s2g(void* dst, uint32_t src, uint32_t bytes) {
    asm volatile("cp.async.bulk.global.shared::cta.bulk_group [%0], [%1], %2;" ::"l"(dst), "r"(src), "r"(bytes) : "memory");
}
__device__ __forceinline__ void bulk_commit() { asm volatile("cp.async.bulk.commit_group;" ::: "memory"); }
__device__ __forceinline__ void bulk_wait() { asm volatile("cp.async.bulk.wait_group 0;" ::: "memory"); }
__device__ __forceinline__ void fence_async_global() { asm volatile("fence.proxy.async.global;" ::: "memory"); }
__device__ __forceinline__ void fence_release() { asm volatile("fence.release.gpu;" ::: "memory"); }
__device__ __forceinline__ void fence_acquire() { asm volatile("fence.acquire.gpu;" ::: "memory"); }
__device__ __forceinline__ void ll_check5(uint4 (&f)[5], const uint4* p, uint32_t mark) {
#define LL_LD(i, a, b, c, d) "ld.relaxed.gpu.global.b128 q, [%20 + " #i "];\nmov.b128 {u, v}, q;\nmov.b64 {%" #a ", %" #b "}, u;\nmov.b64 {%" #c ", %" #d "}, v;\n"
    asm volatile("{\n.reg .pred p;\n.reg .b32 t, n, m;\n.reg .b128 q;\n.reg .b64 u, v;\nmov.u32 n, 0x7FFFF;\n"
                 "L:\nlop3.b32 t, %0, %4, %21, 0x7E;\nlop3.b32 t, t, %8, %21, 0xF6;\nlop3.b32 t, t, %12, %21, 0xF6;\nlop3.b32 t, t, %16, %21, 0xF6;\n"
                 "shr.u32 m, n, 18;\nand.b32 t, t, m;\nsetp.ne.u32 p, t, 0;\nvote.sync.any.pred p, p, 0xffffffff;\n@!p bra.uni D;\n"
                 LL_LD(0, 0, 1, 2, 3) LL_LD(512, 4, 5, 6, 7) LL_LD(1024, 8, 9, 10, 11) LL_LD(1536, 12, 13, 14, 15) LL_LD(2048, 16, 17, 18, 19)
                 "sub.u32 n, n, 1;\nbra.uni L;\nD:\n}"
                 : "+r"(f[0].x), "+r"(f[0].y), "+r"(f[0].z), "+r"(f[0].w), "+r"(f[1].x), "+r"(f[1].y), "+r"(f[1].z), "+r"(f[1].w), "+r"(f[2].x), "+r"(f[2].y),
                   "+r"(f[2].z), "+r"(f[2].w), "+r"(f[3].x), "+r"(f[3].y), "+r"(f[3].z), "+r"(f[3].w), "+r"(f[4].x), "+r"(f[4].y), "+r"(f[4].z), "+r"(f[4].w)
                 : "l"(p), "r"(mark) : "memory");
}
template<int TA, int TB>
__device__ __forceinline__ void wgmma_n192(float (&d)[96], uint64_t da, uint64_t db, int scale_d) {
  asm volatile("{\n.reg .pred p;\nsetp.ne.b32 p, %98, 0;\n"
    "wgmma.mma_async.sync.aligned.m64n192k16.f32.bf16.bf16 "
    "{%0, %1, %2, %3, %4, %5, %6, %7, %8, %9, %10, %11, %12, %13, %14, %15, %16, %17, %18, %19, %20, %21, %22, %23, %24, %25, %26, %27, %28, %29, %30, %31, %32, %33, %34, %35, %36, %37, %38, %39, %40, %41, %42, %43, %44, %45, %46, %47, %48, %49, %50, %51, %52, %53, %54, %55, %56, %57, %58, %59, %60, %61, %62, %63, %64, %65, %66, %67, %68, %69, %70, %71, %72, %73, %74, %75, %76, %77, %78, %79, %80, %81, %82, %83, %84, %85, %86, %87, %88, %89, %90, %91, %92, %93, %94, %95}, %96, %97, p, 1, 1, %99, %100;\n}\n"
    : "+f"(d[0]), "+f"(d[1]), "+f"(d[2]), "+f"(d[3]), "+f"(d[4]), "+f"(d[5]), "+f"(d[6]), "+f"(d[7]), "+f"(d[8]), "+f"(d[9]), "+f"(d[10]), "+f"(d[11]), "+f"(d[12]), "+f"(d[13]), "+f"(d[14]), "+f"(d[15]), "+f"(d[16]), "+f"(d[17]), "+f"(d[18]), "+f"(d[19]), "+f"(d[20]), "+f"(d[21]), "+f"(d[22]), "+f"(d[23]), "+f"(d[24]), "+f"(d[25]), "+f"(d[26]), "+f"(d[27]), "+f"(d[28]), "+f"(d[29]), "+f"(d[30]), "+f"(d[31]), "+f"(d[32]), "+f"(d[33]), "+f"(d[34]), "+f"(d[35]), "+f"(d[36]), "+f"(d[37]), "+f"(d[38]), "+f"(d[39]), "+f"(d[40]), "+f"(d[41]), "+f"(d[42]), "+f"(d[43]), "+f"(d[44]), "+f"(d[45]), "+f"(d[46]), "+f"(d[47]), "+f"(d[48]), "+f"(d[49]), "+f"(d[50]), "+f"(d[51]), "+f"(d[52]), "+f"(d[53]), "+f"(d[54]), "+f"(d[55]), "+f"(d[56]), "+f"(d[57]), "+f"(d[58]), "+f"(d[59]), "+f"(d[60]), "+f"(d[61]), "+f"(d[62]), "+f"(d[63]), "+f"(d[64]), "+f"(d[65]), "+f"(d[66]), "+f"(d[67]), "+f"(d[68]), "+f"(d[69]), "+f"(d[70]), "+f"(d[71]), "+f"(d[72]), "+f"(d[73]), "+f"(d[74]), "+f"(d[75]), "+f"(d[76]), "+f"(d[77]), "+f"(d[78]), "+f"(d[79]), "+f"(d[80]), "+f"(d[81]), "+f"(d[82]), "+f"(d[83]), "+f"(d[84]), "+f"(d[85]), "+f"(d[86]), "+f"(d[87]), "+f"(d[88]), "+f"(d[89]), "+f"(d[90]), "+f"(d[91]), "+f"(d[92]), "+f"(d[93]), "+f"(d[94]), "+f"(d[95])
    : "l"(da), "l"(db), "r"(scale_d), "n"(TA), "n"(TB));
}

template<int TA, int TB>
__device__ __forceinline__ void wgmma_n48(float (&d)[24], uint64_t da, uint64_t db, int scale_d) {
  asm volatile("{\n.reg .pred p;\nsetp.ne.b32 p, %26, 0;\n"
    "wgmma.mma_async.sync.aligned.m64n48k16.f32.bf16.bf16 "
    "{%0, %1, %2, %3, %4, %5, %6, %7, %8, %9, %10, %11, %12, %13, %14, %15, %16, %17, %18, %19, %20, %21, %22, %23}, %24, %25, p, 1, 1, %27, %28;\n}\n"
    : "+f"(d[0]), "+f"(d[1]), "+f"(d[2]), "+f"(d[3]), "+f"(d[4]), "+f"(d[5]), "+f"(d[6]), "+f"(d[7]), "+f"(d[8]), "+f"(d[9]), "+f"(d[10]), "+f"(d[11]), "+f"(d[12]), "+f"(d[13]), "+f"(d[14]), "+f"(d[15]), "+f"(d[16]), "+f"(d[17]), "+f"(d[18]), "+f"(d[19]), "+f"(d[20]), "+f"(d[21]), "+f"(d[22]), "+f"(d[23])
    : "l"(da), "l"(db), "r"(scale_d), "n"(TA), "n"(TB));
}

__device__ __forceinline__ void wgmma_rs80(float (&d)[40], const uint4& a, uint64_t db, int scale_d) {
  asm volatile("{\n.reg .pred p;\nsetp.ne.b32 p, %45, 0;\n"
    "wgmma.mma_async.sync.aligned.m64n80k16.f32.bf16.bf16 {%0,%1,%2,%3,%4,%5,%6,%7,%8,%9,%10,%11,%12,%13,%14,%15,%16,%17,%18,%19,%20,%21,%22,%23,%24,%25,%26,%27,%28,%29,%30,%31,%32,%33,%34,%35,%36,%37,%38,%39}, {%40,%41,%42,%43}, %44, p, 1, 1, 1;\n}\n"
    : "+f"(d[0]), "+f"(d[1]), "+f"(d[2]), "+f"(d[3]), "+f"(d[4]), "+f"(d[5]), "+f"(d[6]), "+f"(d[7]), "+f"(d[8]), "+f"(d[9]), "+f"(d[10]), "+f"(d[11]), "+f"(d[12]), "+f"(d[13]), "+f"(d[14]), "+f"(d[15]), "+f"(d[16]), "+f"(d[17]), "+f"(d[18]), "+f"(d[19]), "+f"(d[20]), "+f"(d[21]), "+f"(d[22]), "+f"(d[23]), "+f"(d[24]), "+f"(d[25]), "+f"(d[26]), "+f"(d[27]), "+f"(d[28]), "+f"(d[29]), "+f"(d[30]), "+f"(d[31]), "+f"(d[32]), "+f"(d[33]), "+f"(d[34]), "+f"(d[35]), "+f"(d[36]), "+f"(d[37]), "+f"(d[38]), "+f"(d[39])
    : "r"(a.x), "r"(a.y), "r"(a.z), "r"(a.w), "l"(db), "r"(scale_d));
}

__device__ __forceinline__ void wgmma_ss80(float (&d)[40], uint64_t da, uint64_t db) {
  asm volatile("wgmma.mma_async.sync.aligned.m64n80k16.f32.bf16.bf16 {%0,%1,%2,%3,%4,%5,%6,%7,%8,%9,%10,%11,%12,%13,%14,%15,%16,%17,%18,%19,%20,%21,%22,%23,%24,%25,%26,%27,%28,%29,%30,%31,%32,%33,%34,%35,%36,%37,%38,%39}, %40, %41, 1, 1, 1, 0, 1;"
    : "+f"(d[0]), "+f"(d[1]), "+f"(d[2]), "+f"(d[3]), "+f"(d[4]), "+f"(d[5]), "+f"(d[6]), "+f"(d[7]), "+f"(d[8]), "+f"(d[9]), "+f"(d[10]), "+f"(d[11]), "+f"(d[12]), "+f"(d[13]), "+f"(d[14]), "+f"(d[15]), "+f"(d[16]), "+f"(d[17]), "+f"(d[18]), "+f"(d[19]), "+f"(d[20]), "+f"(d[21]), "+f"(d[22]), "+f"(d[23]), "+f"(d[24]), "+f"(d[25]), "+f"(d[26]), "+f"(d[27]), "+f"(d[28]), "+f"(d[29]), "+f"(d[30]), "+f"(d[31]), "+f"(d[32]), "+f"(d[33]), "+f"(d[34]), "+f"(d[35]), "+f"(d[36]), "+f"(d[37]), "+f"(d[38]), "+f"(d[39])
    : "l"(da), "l"(db));
}

__device__ const __align__(1024) uint32_t c_fft[11264] = {
0x2ddc2dba,0x2fe62eb5,0x2ed02eb5,0xafffaf6e,0x2e1f2dfe,0x2e3f2fbc,0x2f022ee9,0xad27af30,0x2e5e2e3f,0x1fd92b5e,0x2f302f1a,0x244ea875,0x2e992e7c,0xad96a993,0x2f5a2f46,0x2e992c32,
0xad00ad72,0xa17eac32,0xa17ea515,0xabb79cb6,0xac07ac87,0x2dfe29f1,0x1fd99648,0xafedae99,0xa9f1ab05,0x2fd42fbc,0x26a1244e,0xad96af91,0xa765a8d5,0x2aaa2e3f,0x29932875,0x2515a8d5,
0xae99adfe,0xb000aee9,0xaf6eafbc,0x2c872f30,0xaf80af1a,0xac32af02,0xae7caf02,0xaaaa217e,0xaff4afc9,0x2b5e9cb6,0xad27addc,0xaff4ae7c,0xafedb000,0x2ffc2eb5,0xab05ac5d,0xacd8af5a,
0x2c072d27,0x9fd92bb7,0xadfead00,0x2fed2e1f,0x25db2993,0xaf6eacb0,0xaf6eaed0,0x2c5d2f46,0xa5151648,0xaddcafdd,0xafffafd4,0xac321648,0xabb7a934,0x28d5a814,0xafa0afed,0xaff4af30,
0x2f302e3f,0x2fed2f1a,0x28142b5e,0x2934a875,0x30002fc9,0x26a12ddc,0xa5db1cb6,0x30002e7c,0x2f462fd4,0xaed0aa4e,0xacb0aa4e,0x29932e99,0x2d272e5e,0xae3faffc,0xaf02adfe,0xae1fa814,
0xa9f1acd8,0x26a1ab05,0x2fd42ffc,0xad96afed,0x2515a30e,0x2fff2e1f,0x2ddc2f1a,0x2c32a30e,0x2d272aaa,0x28752e7c,0x28752c32,0x2fa02f80,0x2f912e99,0xaee9a9f1,0xa8141648,0x9fd92c87,
0xafa0ae7c,0xafafaf46,0x2d002993,0xafa0ac32,0xaf91b000,0x244eac5d,0x2fbc2eb5,0xab05af5a,0xac87ae5e,0x30002dfe,0x2f6e2ffc,0x2e992814,0x1cb6a875,0x25152e1f,0x2c322e1f,0x2d722ff4,
0x27652c87,0xa9932a4e,0xaaaaadba,0xa5152c87,0xabb7a44e,0xafa0af30,0x28d59fd9,0xaff4ae5e,0xaf91ae1f,0x2814abb7,0x2ee92d00,0x1fd9ad27,0xaf5aafff,0x2fd42ed0,0x2fd42fe6,0x30002ddc,
0x2f462f6e,0x2c322fdd,0x2e7c2fdd,0xa993b000,0xab5e2934,0xafafacd8,0xad00244e,0x2f1a2dfe,0xaee9afaf,0x2f30a17e,0xadfeaff8,0xafbca30e,0x2c5da765,0xa9f12ddc,0x2d969cb6,0x2c5dacb0,
0x2bb7a993,0x2f1aa515,0x2f1a2765,0xaff4aaaa,0x2e5e2fd4,0xab052dba,0x29342f6e,0x2ee9a6a1,0xadba1fd9,0xa5dbafed,0xafddac07,0xaa4e2dfe,0xacb0aff8,0x2ddc2f02,0x9cb6ae3f,0xa765aff8,
0xaeb5af91,0xaa4eafed,0x9648ae5e,0xac5d2d4d,0x2ddca17e,0x2e7c2e3f,0x2fc92e3f,0x1cb6afa0,0x2bb72fe6,0xaff8a993,0xab5e2aaa,0x2bb72fc9,0xafbcaa4e,0x2f30a5db,0xadfeafdd,0xaee9adba,
0xacd828d5,0xaf91230e,0xaf30af02,0x2c072fa0,0xac5dafff,0x2dbaac32,0x2dbaa515,0xae99addc,0x2fc929f1,0xa9932eb5,0x2aaa2fdd,0x2fe629f1,0xa30e2dfe,0xa17eafed,0xaff8ac07,0xafaf1fd9,
0x2dfe2faf,0x28142ff8,0xae5e217e,0x2ffc230e,0xaf5aa515,0xac87af46,0xa6a1af80,0xaf5a2765,0x1cb6ae99,0x2e7c2dba,0x2fc92dba,0x2ddcac5d,0x2f1a2ee9,0xafafab05,0xad002934,0xab5e2e5e,
0x2dbaa814,0x2fdd9fd9,0x25db2f91,0x2a4eaee9,0x27652faf,0xaf4628d5,0xaf80ae1f,0xa5152faf,0xafa0addc,0x2e3fac32,0x2e3fa515,0xa17eafff,0x2dfea6a1,0xacd82dba,0x244e2f6e,0x29342fd4,
0xad27afc9,0xa30eafff,0x2faf2d72,0xad27ae7c,0x2ffc2a4e,0x28142fdd,0xae5e25db,0x2dfe2dba,0xac5d2c07,0xaa4eaf91,0x9648af30,0xaeb5acd8,0xa993aff4,0x2c322f1a,0x2e7c2f1a,0x2f462bb7,
0xae7c26a1,0xafff1648,0x2d72aa4e,0xafc926a1,0x230eaee9,0x2ff89fd9,0x217e2f91,0x2fafa814,0x2d4d2fa0,0xafed230e,0xae5eaf02,0xaf9128d5,0xb000aaaa,0x2fdda515,0x2fdd2765,0x2f6ea993,
0x9cb63000,0xacb02fd4,0xa7652fd4,0x2ddcaf5a,0x217eaffc,0x2ff4ac07,0x2875afbc,0xaff82934,0xa44e2ff4,0xadfea8d5,0xa9342fa0,0x2cd82bb7,0x25dbafe6,0x16482f46,0x29f1af80,0x25dbafc9,
0x2ff41cb6,0x2e1f2765,0x2e1f2cb0,0xa875addc,0xafbca5db,0x1fd9af5a,0xad4dad96,0xacd82fdd,0x2f5a2934,0xaeb52ee9,0x2c5d2e5e,0x3000ab05,0xaed0ab5e,0x2f80a30e,0xaaaaaf02,0xacb0ab5e,
0x25dbaffc,0x2d96afbc,0x2f5aac07,0xafdd2934,0xaaaa2fa0,0xafc92875,0xafe62875,0x29932d27,0x2d00aed0,0x28d52d72,0x2ff89cb6,0x2d00afe6,0xae5e2d96,0x2d4dafd4,0xaf91a6a1,0xafed29f1,
0xafbca17e,0xad4da875,0x1fd9aff4,0xacd82ff8,0x2e992aaa,0xaa4e2fe6,0xaa4e2fc9,0x2fd4a993,0xacb0ad96,0x2fffac87,0x2d72aeb5,0xa765ad96,0x28752f30,0xab5eac07,0xaf1a2cd8,0xae3f2f91,
0xa9342ff4,0xae5e2fa0,0xaee9a8d5,0x2b052bb7,0x2d96aed0,0x2eb59cb6,0x2c872d72,0x2d96afe6,0xaf802c5d,0x2765af6e,0xa515af6e,0xaf4625db,0x2ff8a44e,0xaff42d4d,0xa8752ffc,0xa17e2ee9,
0x2f5a244e,0x2c5d2934,0xaeb52dfe,0x3000acd8,0xacb0ad00,0x2d72aff8,0x2fffa8d5,0xa765ad00,0x217e2f80,0xaf022515,0xaf02a765,0xaf1a2f46,0x2b05afdd,0xa8142f5a,0x2c072d96,0x2d4d25db,
0x2b5eafe6,0x2f02af80,0x230e2f46,0x2b5eafc9,0xaf302d96,0xacd8a6a1,0x2c07afd4,0xaf9129f1,0x2fdda44e,0xad962ffc,0xaf5a2d4d,0xa5db2ee9,0xad72abb7,0x2e7ca17e,0x2fc9a17e,0x2fffad00,
0xaed0a5db,0xaaaaa9f1,0x2f809648,0xacb0a5db,0x28752e5e,0xaf1a2f91,0xab5ead4d,0xae3f2fed,0x2b05aff8,0x2c072875,0xa8142ff4,0x2d4d217e,0xaf6e2d72,0x2eb5afc9,0x2eb5ae7c,0x2dbaafff,
0xaf802f5a,0xafc92e99,0xafe62e99,0x2f46ad96,0x28d52b05,0xaf022fed,0x230e2cd8,0x2fa0affc,0x2fbcaf02,0xa9342d27,0x2ffcae1f,0x2c07ae3f,0xa6a1ac32,0x2a4e9cb6,0x9648ad72,0xa6a1a515,
0x28752aaa,0xa8d52cb0,0xa8d52ed0,0x2e3faf80,0x2fedaeb5,0x29349648,0x2f30aa4e,0x2814ac5d,0x1648ad4d,0x2e99acd8,0x2c87afbc,0xa9f11fd9,0xafe62d27,0x2fffafaf,0xaddc230e,0xaed02d27,
0x2fd4af30,0x2f6eae5e,0x2dbaa44e,0xa6a19fd9,0x1cb6ad27,0x2fe6aff4,0x2ed0aff4,0xad722b5e,0xafaf2cb0,0x2e1faf46,0xa8d5a993,0xafaf2ed0,0xac072f6e,0x2934ac87,0xaffc2e99,0xafbc3000,
0xa44eab5e,0x2b05ad00,0x2f91afaf,0xafbc2f1a,0xafd42d72,0x1648a765,0x1648acb0,0xafdd2fff,0xac322f5a,0xaaaa26a1,0xaf802c87,0xae7c2f5a,0x2d009fd9,0xae1f2cd8,0xad272fbc,0xabb72d4d,
0xaffc2f02,0xaee92e1f,0x244ead27,0xad4d2e3f,0xa9f12e7c,0xafdd2f80,0xaeb52aaa,0xa9f12c32,0x2d72a5db,0xafe63000,0xaed03000,0x9cb626a1,0x2fa0afbc,0xaf022f91,0x230e2b05,0x28d5a44e,
0x96482c07,0xac872d4d,0xae992b05,0x29f1a814,0x2ed0abb7,0xa9932b5e,0xaf462ff8,0x2cb0abb7,0x2f1aafff,0xa30e2765,0xa30e2cb0,0x2e1fad72,0x1fd9ac5d,0x244e9648,0x2e5eaa4e,0x2f30aeb5,
0x2ff8aed0,0x2e3faddc,0xaf022fff,0x2ff8afe6,0x2d4daf6e,0x2ee9ae99,0xa44e2c87,0x2ffcb000,0xa6a1a814,0x2f6eaf30,0x2dbaa934,0x2fd4afed,0xaf462d00,0x2fc9afa0,0x2fe6afa0,0x2f80afaf,
0x2515ac5d,0x2d72ad96,0x1cb629f1,0x2c32ac5d,0xad002814,0x2d27ad4d,0x2e1fab05,0x2bb7ac07,0xaffc2f1a,0x2cd8ad00,0x2fedafaf,0x2b05ab5e,0xadba2f80,0x2c87acb0,0x2c87aed0,0x2a4eaaaa,
0x2f802f6e,0x2fc92fdd,0x2fe62fdd,0xaf46b000,0x2fa02f91,0x2bb72e5e,0x2ff42fed,0xa8d5ad4d,0x2fbc2faf,0xa934217e,0x2ffc2ff8,0x2c07230e,0x2fd42fc9,0xaf5aad72,0x30002fff,0x2fd42e7c,
0x2bb72aaa,0x2f1a2cb0,0x2f1a2ed0,0xaff4af80,0x2cd82c5d,0x2f303000,0x2f912f5a,0xac07aeb5,0x2dba2d4d,0x25db2cd8,0x2fdd2fbc,0x2a4e9fd9,0x2e7c2e1f,0xad72a875,0x2fff2ff4,0x2fc92e1f,
0xa6a1a934,0x29f1a44e,0x2d962cd8,0xafd4adfe,0x1cb6a17e,0x2fe62e3f,0x2ed02e3f,0xad72afa0,0x28752515,0x2d272f80,0x2fa02f46,0x2875a765,0x2c072a4e,0xa93425db,0x2ffc2fdd,0x2fbc2dba,
0xae5eaf1a,0xa934ae3f,0x2b052875,0xaee9ab5e,0xac5dad72,0x2dba2765,0x2dba2cb0,0xae99afff,0xa765aa4e,0x2f802fd4,0x2f462e99,0x2515aa4e,0x230e9fd9,0x217e2cd8,0x2ff82fbc,0x2faf2d4d,
0xaffcafaf,0xaee9aff8,0x244ea17e,0xad4da30e,0xaf6eafe6,0x25dbaaaa,0x2c5d2993,0xaf6eafc9,0xad72ae99,0x2fe62dba,0x2ed02dba,0x1cb6ac5d,0xa8d5ac07,0x2bb72f30,0x2ff42f91,0x2fa02cd8,
0xadbaac07,0xafddad4d,0xa5dbab05,0xaa4e2814,0xafc9af02,0xaaaaaf1a,0x2993217e,0xafe6af02,0xafa0afff,0x2e3f2765,0x2e3f2cb0,0xa17ead72,0xad4daeb5,0x2e5e3000,0x2fed2f5a,0x2f912c5d,
0xa17e2765,0xad001cb6,0xabb7addc,0xa17e2cb0,0xad4daa4e,0xaee9afdd,0x244ea5db,0xaffcadba,0xafd4aee9,0x29f1a934,0x2d962b05,0xa6a1ae5e,0xaf46aff4,0x2fc92f1a,0x2fe62f1a,0x2f802bb7,
0x2cb02eb5,0x1cb62dba,0xaddcaf6e,0x27652eb5,0xa30e2814,0xaff8ad4d,0xa17eab05,0xafafac07,0xadfeab5e,0xa44eae3f,0x2cd82875,0xa934af1a,0xb000af80,0x2fdd2cb0,0x2fdd2ed0,0x2f6e2aaa,
0x2d723000,0x25152fd4,0x2c322fd4,0x1cb6af5a,0xae1f9fd9,0xae3faee9,0xaf02a814,0x2d272f91,0xacd8aff4,0x2ffc28d5,0xab05afa0,0xafedabb7,0x2e992515,0xad962aaa,0x2f5a2993,0x2e99a765,
0x2ff42ddc,0x2e1f2ed0,0x2e1f2fe6,0xa875afff,0xa8142c87,0xaffca9f1,0xadfe1648,0x2e5e2e99,0xaf5aaf30,0x2eb5a814,0xac5dafed,0xb000a934,0x2c32a8d5,0xa9932e3f,0x2f462875,0x2e7ca8d5,
0x2e991fd9,0x30002814,0x2f6e2ee9,0xac87af91,0x29932fa0,0xaed02875,0xacb02875,0x2f462d27,0xaff4ac32,0x2b5eaddc,0xad27afff,0xaff4a515,0x244ead96,0x1fd92fd4,0x2f3026a1,0x2e5ea9f1,
0x2814ad27,0x2dfeabb7,0x2ffc2d00,0xae5eae1f,0x2e992f80,0xaa4e2e7c,0xaa4e2c32,0x2fd42aaa,0xae7c1648,0x9cb6afdd,0xaddcafd4,0xafc91648,0xa875af91,0x2b5e2fbc,0x2f1a244e,0x2e3fab05,
0xab05aff4,0x244eafa0,0x2fbc28d5,0xaf91abb7,0x30002c32,0x26a12fff,0xa5db2ddc,0x30002515,0xaaaa2c5d,0xac32af6e,0xae7caf6e,0xaf8025db,0xad27afed,0x2e3f2dfe,0x2f021fd9,0x2e1fac07,
0xaf5aae5e,0xac5daf30,0x2eb59fd9,0xb000a44e,0x2e7ca30e,0x2ddc2e1f,0x1cb62f1a,0x2fc9a30e,0x217e2f46,0xaf02acb0,0xaf02aed0,0xaf1a2993,0xaf30ae99,0x2fbc29f1,0x2ee99648,0x2dfeac87,
0xafa0a515,0xafafa993,0x2d00aaaa,0xafa02765,0x2934ad96,0x2fed26a1,0x28142fd4,0x2f30a9f1,0x2c872fed,0xb0009fd9,0xaf6eadfe,0xae992c07,0xafffabb7,0x2fe6a17e,0x2ed0a17e,0x2ddcad00,
0xac322c87,0xaf462a4e,0x2993adba,0xae7c2c87,0xa875afed,0x2f1aab05,0x2b5e2ffc,0x2e3facd8,0x2f302e1f,0xaee92bb7,0xafbcad00,0xadfe2d27,0xaf6e9cb6,0x2eb5ac32,0x2eb5a515,0x2dbaad72,
0xaaaa2f5a,0xaed02e99,0xacb02e99,0x2f80ad96,0x2b5eaf30,0x2fafa44e,0x2d00ae5e,0xaf1a9fd9,0xac072f02,0xab05ad27,0xad4d2e1f,0x28142e3f,0x2c5daed0,0xa9f12fff,0x2d96addc,0x2c5dafe6,
0x28752f80,0xa8d52fe6,0xa8d52fc9,0x2e3faf46,0xa44eafd4,0x2f91adba,0x2b05af6e,0xafbc26a1,0x96482ffc,0xae99a44e,0xac872ee9,0x29f12d4d,0x2515aff8,0x1cb62f02,0x2d72ae3f,0x2c32aff8,
0x2eb52b05,0x2a4e2cd8,0x16482fed,0x2c5daffc,0xad72ad27,0x2cb0aff4,0x2765aff4,0xafff2b5e,0x2bb72e7c,0xaff82aaa,0xab5e2f80,0x2bb72c32,0xa814af6e,0x2b052c87,0x2d4dae99,0x2c07b000,
0x2feda8d5,0x2f30a30e,0x29342f02,0x2814afa0,0xafd49cb6,0x1648aed0,0x1648afe6,0xafdd2d72,0x2ed029f1,0xaf462eb5,0xa9932fdd,0x2cb029f1,0xad00ad4d,0x2e1f244e,0x2d27aee9,0x2bb7affc,
0x2d4daf02,0x2fbcae1f,0x2cd82d27,0x9fd9ae3f,0xaf5a2cb0,0xac87a993,0xa6a1af46,0xaf5a2ed0,0x2fffa5db,0xacb03000,0xa7653000,0x2d7226a1,0xaf1aa814,0x2fafa934,0x2d00af30,0x2b5eafed,
0x1648afbc,0x2c87affc,0x2e992934,0xa9f1ac07,0xac322faf,0xaf8028d5,0xaaaaae1f,0xae7c2faf,0x2f1aad72,0xa30e2ed0,0xa30e2fe6,0x2e1f1cb6,0xaffc26a1,0x2fedadba,0x2cd8af6e,0x2b05afd4,
0xad27ac32,0xa30ead72,0x2faf9cb6,0xad27a515,0x1fd92f6e,0xafbc2e99,0xacd8ac87,0xad4d3000,0x2c5dafbc,0x2a4e2b05,0x16482f91,0x2eb5a44e,0xaf802d00,0x2ed0afa0,0x2cb0afa0,0x2aaaafaf,
0xafe626a1,0xaddc1648,0x2fffaa4e,0xaed026a1,0x2d002c07,0xad272ffc,0xae1fa934,0xabb72fbc,0x1fd9afa0,0x2e5ea30e,0x244e2f02,0x2f30a8d5,0xadba2f46,0x2c87afe6,0x2c87afc9,0x2a4eaf80,
0xafff2d96,0xae7c2c5d,0xafc92c5d,0x2d72a9f1,0xa17e2dfe,0xaff42fbc,0xa8752ee9,0x2ff8af30,0x2fedad00,0xad4d2f1a,0x2f91ab5e,0x2e5eafaf,0x25dbae7c,0x16482993,0x29f1af46,0x25dbac32,
0xae3f2fff,0xaff82fc9,0xaff82e7c,0x2f02ad72,0x2c0725db,0xadfe2f5a,0x9fd92d96,0x2fedafdd,0x2f6eaf91,0xa6a12c07,0x2fd4acd8,0x2dbaaf30,0xa765ab5e,0x2aaaa30e,0x2993af02,0x2515ab5e,
0xa5db2dfe,0xad962ee9,0xaf5a2fbc,0x2fddaf30,0x2f46ab5e,0xa7652bb7,0x25152bb7,0x2f80aff8,0x2d00afc9,0x28d59cb6,0x2ff8addc,0x2d00ae7c,0xacd89648,0x2dfeac5d,0x2934aeb5,0x244eaa4e,
0x2c07217e,0x9fd92875,0xadfe2ff4,0x2fedaff8,0x2fddaf46,0x29f1a515,0x29f12765,0x2eb5af80,0x2515ad96,0x2ddcac87,0x2fffaeb5,0x2c32ad96,0xaf022b05,0x2fa0aee9,0x28d5ae5e,0x230ea934,
0x2f91ad00,0x2cd8ab5e,0xac072f1a,0x2f30afaf,0x2d96afc9,0x2eb5addc,0x2c879cb6,0x2d96ae7c,0xa993a6a1,0x2fc9af5a,0x2fe6af5a,0x2aaaac87,0xaff82e5e,0x2ff4affc,0x2875adfe,0x217ea814,
0x2f6eafed,0x2fd4af91,0xa6a12d4d,0x2dbaae5e,0x2515ad00,0x2fffaff8,0x2ddca8d5,0x2c32ad00,0xae1f2993,0x2fafafe6,0x2fafafc9,0x28d5aaaa,0xaf912fdd,0x2ee9af5a,0x2814ad96,0x1fd9a5db,
0x2b5eae7c,0x2f02af46,0x230e2993,0x2b5eac32,0xab059648,0x2e5eaeb5,0x2ee9ac5d,0x2934aa4e,0xafdd2e5e,0x2d96adfe,0x2f5aaffc,0x25dba814,0xaddc2faf,0x2cb0ad27,0x2765ad27,0x1cb6a30e,
0xa765a5db,0x2993a9f1,0x2aaa9648,0x2515a5db,0xaf022cd8,0x28d5a934,0x2fa0adfe,0x230ea44e,0xaf912ff8,0x2814a875,0x2ee9aff4,0x1fd9a17e,0xaa4e2ddc,0x26a1a765,0x26a1acb0,0x16489cb6,
0x2d722d96,0x25152c5d,0x2c322c5d,0x1cb6a9f1,0x2d272d4d,0xad00a814,0x2bb72c07,0x2e1f2b05,0x2cd82d00,0xaffcaf1a,0x2b052b5e,0x2fed2faf,0x2c872cb0,0xadbaaf80,0x2a4e2aaa,0x2c872ed0,
0x2e3f2ddc,0x2ff82ed0,0x2ff82fe6,0xaf02afff,0x2ee92e99,0x2d4d2f6e,0x2ffc3000,0xa44eac87,0x2f6e2f30,0xa6a12814,0x2fd42fed,0x2dba2934,0x2fc92fa0,0xaf46ad00,0x2f802faf,0x2fe62fa0,
0xac87ad4d,0x9648ac07,0x29f12814,0xae99ab05,0xa993ab5e,0x2ed02bb7,0x2cb02bb7,0xaf46aff8,0xa30ea765,0x2f1a2fff,0x2e1f2d72,0xa30eacb0,0x244e1648,0x1fd92c5d,0x2f302eb5,0x2e5e2a4e,
0xaee9ae1f,0xaffcaf02,0xad4dae3f,0x244e2d27,0xafddaf80,0xa9f1ae7c,0xa9f1ac32,0xaeb5aaaa,0xafe6b000,0x2d7225db,0x9cb6a6a1,0xaed0b000,0xaf02af91,0x2fa02fbc,0x28d5244e,0x230eab05,
0x2b052d00,0xa44e2b5e,0xafbcaf1a,0x2f912faf,0x16482765,0xafd4ad72,0xafddafff,0x16482cb0,0xaaaaa6a1,0xac32af5a,0xae7caf5a,0xaf80ac87,0xae1facd8,0x2d001fd9,0xabb7ad4d,0xad27afbc,
0x2f6e2e5e,0x2fd42f30,0xa6a11fd9,0x2dba244e,0x2fe62ff4,0x1cb62d27,0xad72ab5e,0x2ed02ff4,0x2e1f2f46,0xafafacb0,0xafafaed0,0xa8d52993,0x29342c87,0xac07af6e,0xafbcb000,0xaffcae99,
0xa8d5acb0,0x2875aaaa,0x2e3f2f80,0xa8d5aed0,0x29341648,0x2fed2eb5,0x28142c5d,0x2f302a4e,0x2e992cd8,0x16482d4d,0xa9f19fd9,0x2c872fbc,0x2fff2faf,0xafe6ad27,0xaed0ad27,0xaddca30e,
0xafc9ae99,0xaf80af5a,0x2f462d96,0xafe6ae99,0xaf02afed,0x28d5ab05,0x2fa02ffc,0x230eacd8,0xa934ad27,0x2fbc2f02,0x2c072e3f,0x2ffc2e1f,0x2a4e1cb6,0xa6a12c32,0xa6a12515,0x96482d72,
0xaaaa29f1,0xaed025db,0xacb025db,0x2f801648,0xaf1aaf91,0x2875ae5e,0xae3fafed,0xab5e2d4d,0x2c07a875,0x2b052ff8,0x2d4da17e,0xa814aff4,0x2eb52fc9,0xaf6ead72,0x2dba2fff,0x2eb52e7c,
0x2f022f80,0x2b5e2fe6,0x2b5e2fc9,0x230eaf46,0xacd826a1,0xaf30ad96,0xaf91a9f1,0x2c072fd4,0xad96affc,0x2fdd244e,0xa5dbaee9,0xaf5aad4d,0x2e7c217e,0xad722bb7,0x2fff2d00,0x2fc9217e,
0x2c5da934,0x2f5aa44e,0x30002cd8,0xaeb5adfe,0x2d722ff8,0xacb02d00,0xa7652d00,0x2fff28d5,0xaf02a515,0x217eaf80,0xaf1aaf46,0xaf022765,0xa814af5a,0x2b052fdd,0x2d4da5db,0x2c07ad96,
0xae5eafa0,0xa934aff4,0x2b05abb7,0xaee928d5,0x2eb51cb6,0x2d962ed0,0x2d962fe6,0x2c87ad72,0x27652f6e,0xaf80ac5d,0xaf46a5db,0xa5152f6e,0xaff4ad4d,0x2ff8244e,0xa17eaee9,0xa875affc,
0xad4d2875,0xafbc217e,0xacd8aff8,0x1fd92ff4,0xaa4eafe6,0x2e99aaaa,0x2fd42993,0xaa4eafc9,0x2fff2c87,0xacb02d96,0xa7652d96,0x2d722eb5,0xab5e2c07,0x2875af30,0xae3faf91,0xaf1aacd8,
0x2d962fbc,0x25db2ffc,0xafdda934,0x2f5a2c07,0xafc9a875,0xaaaaafa0,0x2993ad27,0xafe6a875,0x28d5ad72,0x2d002ed0,0x2d002fe6,0x2ff81cb6,0x2d4d2fd4,0xae5ead96,0xafeda9f1,0xaf9126a1,
0x2e1fa765,0x2ff49cb6,0xa8752ddc,0x2e1facb0,0x1fd92f5a,0xafbc25db,0xacd8afdd,0xad4d2d96,0xaeb5aee9,0x2f5aa934,0x30002b05,0x2c5dae5e,0x2f80230e,0xaed02b5e,0xacb02b5e,0xaaaa2f02,
0xacb0afd4,0x9cb6b000,0x2ddc2f5a,0xa765afd4,0x2ff42c07,0x217e2ffc,0xaff8a934,0x28752fbc,0xadfe28d5,0xa44eaff4,0x2cd8abb7,0xa934afa0,0x1648af46,0x25db2fe6,0x25db2fc9,0x29f12f80,
0xafff9648,0xae7ca6a1,0xafc9a6a1,0x2d722a4e,0x2ff81fd9,0x230e2ee9,0x2faf2814,0x217eaf91,0xafeda30e,0x2d4dafa0,0xaf91a8d5,0xae5e2f02,0x2fdd2515,0xb0002aaa,0x2f6e2993,0x2fdda765,
0xa30e2fff,0xad272fc9,0xad272e7c,0x2fafad72,0x2814afdd,0x2ffcaa4e,0x2dfeadba,0xae5ea5db,0xaa4e2f91,0xac5dac07,0xaeb52cd8,0x96482f30,0x2c32af1a,0xa9932ff4,0x2f46abb7,0x2e7caf1a,
0x2fdd1fd9,0x2dba2814,0x2a4e2ee9,0x25dbaf91,0xaf46a8d5,0x2765afaf,0xa515afaf,0xaf802e1f,0x2e3f2c32,0xafa02ddc,0xa17e2fff,0x2e3f2515,0xacd8adba,0x2dfe26a1,0x2934afd4,0x244eaf6e,
0x2814aff8,0x2dfeafaf,0x2ffca30e,0xae5ea17e,0xac872f46,0xaf5a2515,0xaf5aa765,0xa6a12f80,0x2e7cadba,0x1cb62e99,0x2ddc2c5d,0x2fc9adba,0xafaf2b05,0x2f1aaee9,0xab5eae5e,0xad00a934,
0xaf91a30e,0xacd8a8d5,0x2c07afa0,0xaf302f02,0x2dba2c32,0xac5d2fff,0xae992ddc,0x2dba2515,0xa993aeb5,0x2fc9a9f1,0x2fe6a9f1,0x2aaaafdd,0xa17e2fed,0xa30eadfe,0xafaf9fd9,0xaff82c07,
0xaa4e2fed,0xaeb52f91,0xac5dad4d,0x96482e5e,0x2e7cae3f,0x2ddc217e,0x1cb62fa0,0x2fc9ae3f,0xaff82993,0x2bb7afe6,0x2bb7afc9,0xab5eaaaa,0x2f3025db,0xafbc2a4e,0xaee92dba,0xadfe2fdd,
0x2f1a2515,0x2bb72993,0xaff42aaa,0x2f1aa765,0xab05adba,0x2e5eafd4,0x2ee926a1,0x2934af6e,0xa5db2fed,0xadba9fd9,0xaa4eadfe,0xafdd2c07,0x2ddcaf02,0xacb02ff8,0xa7652ff8,0x9cb62e3f,
0x2c32afdd,0x2f46af6e,0xa9933000,0x2e7cafdd,0xafaf2cd8,0xab5ea934,0x2f1aadfe,0xad00a44e,0x2f30217e,0xaee92faf,0xafbc230e,0xadfe2ff8,0xa9f1addc,0x2c5d2765,0x2c5d2cb0,0x2d961cb6,
0xa993aa4e,0x2765ac87,0xa515ac87,0xaaaa2dba,0xafa02f30,0xabb7244e,0xaff42e5e,0x28d51fd9,0x28142bb7,0xaf912e1f,0x1fd92d27,0x2ee9ad00,0x2fd4aed0,0xaf5a2fff,0x3000addc,0x2fd4afe6,
0xafaf2f46,0xafa02e7c,0xafa02c32,0x2d00a993,0x244e2c5d,0xaf913000,0xab052f5a,0x2fbcaeb5,0x3000adfe,0xac872e5e,0x2e99a814,0x2f6eaffc,0x2515ae1f,0x1cb62875,0x2d72aff4,0x2c32ae1f,
0x26a12b05,0xa9f12cd8,0xad962fed,0x2fd4affc,0x2fffae1f,0x2515230e,0x2c32230e,0x2ddcaf1a,0x2875ae7c,0x2d27aaaa,0x2fa0af80,0x2875ac32,0xaee929f1,0x2f91ae99,0x9fd9ac87,0xa8149648,
0x2fedaf1a,0x2f30ae3f,0x29342875,0x2814ab5e,0x26a1addc,0x3000afc9,0x3000ae7c,0xa5db9cb6,0xaed02a4e,0x2f46afd4,0x2993ae99,0xacb02a4e,0xae3f2ffc,0x2d27ae5e,0xae1f2814,0xaf022dfe,
0x9fd9abb7,0x2c07ad27,0x2fedae1f,0xadfe2d00,0xaf6e2cb0,0x25dba993,0x2c5daf46,0xaf6e2ed0,0xaddc2fdd,0xa5159648,0xac329648,0xafff2fd4,0x28d52814,0xabb72934,0xaff42f30,0xafa02fed,
0xb0002ee9,0xae992dfe,0x2c87af30,0xaf6e2fbc,0xac322f02,0xaf802f1a,0xaaaaa17e,0xae7c2f02,0x2b5e1cb6,0xaff42fc9,0xaff42e7c,0xad272ddc,0x2ffcaeb5,0xafed3000,0xacd82f5a,0xab052c5d,
0xa17e2c32,0xad002d72,0xabb71cb6,0xa17e2515,0x2dfea9f1,0xac072c87,0xafed2e99,0x1fd91648,0x2fd4afbc,0xa9f12b05,0xad962f91,0x26a1a44e,0x2aaaae3f,0xa76528d5,0x251528d5,0x2993a875,
0x2fe6aeb5,0x2ddcadba,0xafff2f6e,0x2ed0aeb5,0x2e3fafbc,0x2e1fadfe,0xad272f30,0x2f02aee9,0x1fd9ab5e,0x2e5eae3f,0x244e2875,0x2f30af1a,0xad962993,0x2e99ae7c,0x2e99ac32,0x2f5aaf46,
0x299329f1,0xa76525db,0x251525db,0x2aaa1648,0x28d52934,0xaf02acd8,0x230e244e,0x2fa02dfe,0x28142875,0xaf91aff8,0x1fd9217e,0x2ee92ff4,0x26a12765,0xaa4eaddc,0x16481cb6,0x26a12cb0,
0x2f022f46,0x2b5e2e7c,0x2b5e2c32,0x230ea993,0x2e5e2eb5,0xab051648,0x29342a4e,0x2ee92c5d,0x2d962dfe,0xafddae5e,0x25db2814,0x2f5a2ffc,0x2cb02d27,0xaddcafaf,0x1cb6230e,0x27652d27,
0x2fd42f91,0x2f6e2fed,0x2dba2e5e,0xa6a1ad4d,0x2fff2ff8,0x25152d00,0x2c322d00,0x2ddc28d5,0x2faf2fe6,0xae1fa993,0x28d52aaa,0x2faf2fc9,0x2ee92f5a,0xaf91afdd,0x1fd925db,0x28142d96,
0x2cd82b5e,0x2f912d00,0x2f302faf,0xac07af1a,0x2eb52ddc,0x2d962fc9,0x2d962e7c,0x2c871cb6,0x2fc92f5a,0xa99326a1,0x2aaa2c87,0x2fe62f5a,0x2ff42ffc,0xaff8ae5e,0x217e2814,0x28752dfe,
0x9fd9a875,0x2c07a17e,0x2fed2ff8,0xadfeaff4,0x29f12515,0x2fdd2f46,0x2eb52f80,0x29f1a765,0x2ddc2c87,0x25152d96,0x2c322d96,0x2fff2eb5,0x2fa02ee9,0xaf02ab05,0x230e2934,0x28d52e5e,
0xad96aee9,0xa5dbadfe,0x2fdd2f30,0xaf5aafbc,0xa765abb7,0x2f462b5e,0x2f802ff8,0x2515abb7,0x28d51cb6,0x2d002fc9,0x2d002e7c,0x2ff82ddc,0x2dfe2c5d,0xacd81648,0x244e2a4e,0x29342eb5,
0xaff8afc9,0xae3fafff,0x2f022d72,0xaff8ae7c,0xadfeaf5a,0x2c07a5db,0x2fed2fdd,0x9fd9ad96,0xa6a1ac07,0x2f6e2f91,0x2dba2f30,0x2fd42cd8,0x2aaa230e,0xa7652b5e,0x25152b5e,0x29932f02,
0xae7cac5d,0xafffad96,0x2d7229f1,0xafc9ac5d,0xaff4afbc,0xa17eadfe,0x2ff82f30,0xa875aee9,0xad4daf1a,0x2fed2d00,0x2e5e2faf,0x2f912b5e,0x1648a993,0x25db2e7c,0x25db2c32,0x29f12f46,
0xaddc9648,0xafe6a6a1,0xaed0a6a1,0x2fff2a4e,0xad27affc,0x2d00ac07,0xabb7afbc,0xae1f2934,0x2e5e230e,0x1fd92fa0,0x2f3028d5,0x244eaf02,0x2c872fe6,0xadbaaf46,0x2a4e2f80,0x2c872fc9,
0xa30e2d72,0xad272c32,0xad272515,0x2faf1cb6,0xafbcae99,0x1fd9af6e,0xad4db000,0xacd82c87,0x2a4eab05,0x2c5d2fbc,0x2eb5244e,0x1648af91,0x2ed02fa0,0xaf80ad00,0x2aaa2faf,0x2cb02fa0,
0x2c872ffc,0x16482fbc,0xa9f12c07,0x2e99a934,0xaf80a8d5,0xac32afaf,0xae7cafaf,0xaaaa2e1f,0xa30eaed0,0x2f1a2d72,0x2e1f9cb6,0xa30eafe6,0x2fed2dba,0xaffca6a1,0x2b052fd4,0x2cd82f6e,
0x2fbc2e1f,0x2d4d2f02,0x9fd92e3f,0x2cd8ad27,0xac872993,0xaf5aacb0,0xaf5aaed0,0xa6a12f46,0xacb0b000,0x2fff25db,0x2d72a6a1,0xa765b000,0x2faf2934,0xaf1a2814,0x2b5e2fed,0x2d002f30,
0x2f30230e,0x2fed28d5,0x28142fa0,0x2934af02,0x16482ed0,0xafd41cb6,0xafddad72,0x16482fe6,0xaf46aeb5,0x2ed0a9f1,0x2cb0a9f1,0xa993afdd,0x2e1fa44e,0xad002d4d,0x2bb72ffc,0x2d272ee9,
0x2a4eacd8,0x2eb5ab05,0x2c5d2ffc,0x1648afed,0x2cb02ff4,0xad722d27,0xafffab5e,0x27652ff4,0xaff8aaaa,0x2bb7ae7c,0x2bb7ac32,0xab5eaf80,0x2b05ac87,0xa8142f6e,0x2c073000,0x2d4d2e99,
0xa8d5afe6,0x2875af80,0x2e3f2f46,0xa8d5afc9,0x2f912dba,0xa44e2fd4,0xafbca6a1,0x2b052f6e,0xae99244e,0x9648affc,0x29f1ad4d,0xac87aee9,0x1cb6af02,0x25152ff8,0x2c322ff8,0x2d722e3f,
0xaed0ae99,0xaaaaaf5a,0x2f802d96,0xacb0ae99,0x2faf244e,0x2b5e2f30,0xaf1a1fd9,0x2d002e5e,0xab052d27,0xac07af02,0x2814ae3f,0xad4dae1f,0xa9f1afff,0x2c5d2ed0,0x2c5d2fe6,0x2d962ddc,
0xaf46aa4e,0xac32ac87,0xae7cac87,0x29932dba,0x2f1a2b05,0xa8752fed,0x2e3f2cd8,0x2b5eaffc,0xaee9abb7,0x2f30ae1f,0xadfead27,0xafbc2d00,0x2eb52c32,0xaf6e1cb6,0x2dba2d72,0x2eb52515,
0xafaf2993,0xafa02515,0xafa0a765,0x2d002aaa,0x2feda6a1,0x29342d96,0x2f3029f1,0x2814afd4,0xb0001fd9,0x2c87afed,0xae99ac07,0xaf6e2dfe,0x2fe6217e,0xafff2bb7,0x2ddc2d00,0x2ed0217e,
0xac5d2f30,0xaf5a2e5e,0xb000244e,0x2eb51fd9,0x2ddcae1f,0x2e7c230e,0x2fc9230e,0x1cb6af1a,0xaf022cb0,0x217eaf46,0xaf1aa993,0xaf022ed0,0x2fbca9f1,0xaf302e99,0x2dfe2c87,0x2ee91648,
0x244e2fa0,0xab052ff4,0xaf912bb7,0x2fbca8d5,0x26a1afff,0x3000ac32,0x3000a515,0xa5dbaddc,0xac322f6e,0xaaaaac5d,0xaf80a5db,0xae7c2f6e,0x2e3fadfe,0xad272fed,0x2e1f2c07,0x2f029fd9,
0x2dfe2bb7,0x28142d27,0xae5e2e1f,0x2ffcad00,0xaa4eae7c,0x2e99af80,0x2fd4aaaa,0xaa4eac32,0x9cb62fdd,0xae7c9648,0xafc99648,0xaddc2fd4,0x2b5eafbc,0xa8752f91,0x2e3f2b05,0x2f1aa44e,
0x3000a814,0x2e999fd9,0xac872f91,0x2f6eaee9,0xaed0a875,0x2993afa0,0x2f46ad27,0xacb0a875,0x2b5e2ddc,0xaff42c32,0xaff42515,0xad272fff,0x1fd9afd4,0x244e2d96,0x2e5e29f1,0x2f30a6a1,
0x2e1faed0,0x2ff4addc,0xa8752fff,0x2e1fafe6,0xaffc29f1,0xa814ac87,0x2e5eae99,0xadfe9648,0x2eb52814,0xaf5a2f30,0xb0002934,0xac5d2fed,0xa993ae3f,0x2c3228d5,0x2e7c28d5,0x2f46a875,
0x2515afd4,0x2d72b000,0x1cb62f5a,0x2c32afd4,0xae3f2ee9,0xae1f1fd9,0x2d27af91,0xaf022814,0x2ffca8d5,0xacd82ff4,0xafed2bb7,0xab052fa0,0xad96aaaa,0x2e99a515,0x2e992765,0x2f5aa993,
0x1cb6adba,0x2cb0aeb5,0x2765aeb5,0xaddc2f6e,0xaff82d4d,0xa30ea814,0xafaf2c07,0xa17e2b05,0xa44e2e3f,0xadfe2b5e,0xa9342f1a,0x2cd8a875,0x2fddacb0,0xb0002f80,0x2f6eaaaa,0x2fddaed0,
0xad009cb6,0xa17ea765,0xa17eacb0,0xabb72ddc,0xaee92fdd,0xad4d2a4e,0xaffc2dba,0x244e25db,0x29f12934,0xafd42ee9,0xa6a12e5e,0x2d96ab05,0x2fc9af1a,0xaf462ff4,0x2f80abb7,0x2fe6af1a,
0xafdd2d4d,0xadba2c07,0xaa4ea814,0xa5db2b05,0xaaaa2f1a,0xafc92f02,0xafe62f02,0x2993a17e,0x2e3fa765,0xafa02fff,0xa17e2d72,0x2e3facb0,0x2e5eb000,0xad4d2eb5,0x2f91ac5d,0x2fedaf5a,
0xaee92ff8,0xaffc2faf,0xad4d230e,0x244e217e,0x25db2aaa,0xaf6e2fe6,0xaf6e2fc9,0x2c5da993,0x2fe6adba,0xad722e99,0x1cb62c5d,0x2ed0adba,0x2bb7af30,0xa8d52c07,0x2fa0acd8,0x2ff4af91,
0xa9342e3f,0xae5e2f1a,0xaee92b5e,0x2b05a875,0x2dbaa765,0xac5d2d72,0xae992fff,0x2dbaacb0,0x2f80afd4,0xa7652a4e,0x25152a4e,0x2f46ae99,0x217eacd8,0x230e1fd9,0x2fafad4d,0x2ff8afbc,
0x29f1244e,0xa6a12934,0xafd42dfe,0x2d96acd8,0x2fe6ae3f,0x1cb6217e,0xad722fa0,0x2ed0ae3f,0x2d27af80,0x2875a515,0x28752765,0x2fa0af46,0xa934a5db,0x2c07aa4e,0x2fbcadba,0x2ffcafdd,
0x2f1aacb0,0x2bb7aaaa,0xaff42f80,0x2f1aaed0,0x2f30b000,0x2cd8ac5d,0xac072eb5,0x2f91af5a,0x25dbacd8,0x2dbaad4d,0x2a4e1fd9,0x2fddafbc,0xad722875,0x2e7cae1f,0x2fc9ae1f,0x2fffaff4,
0x2fc9afdd,0x2f80af6e,0xaf463000,0x2fe6afdd,0x2bb7ae5e,0x2fa0af91,0xa8d52d4d,0x2ff4afed,0xa934a17e,0x2fbcafaf,0x2c07a30e,0x2ffcaff8,0xaf5a2d72,0x2fd4afc9,0x2fd4ae7c,0x3000afff,
0x9d4d9e16,0xada6ae7d,0x9b769c84,0xabf0accf,0x985299e4,0xa897aa43,0x90b6957f,0xa102a5d8,0x13db0a48,0x242c1aad,0x191b1712,0x296d2783,0x1c201aad,0x2c632b1a,0x1db21ce9,0x2e112d3a,
0xa3f4a491,0xae51af42,0xa199a2c6,0xac70ad60,0x9e7ba06b,0xa922ab00,0x97129c20,0xa199a688,0x19e410b6,0x24aa1b76,0x1fa81d4d,0x2a112833,0x222f2102,0x2ce82bf0,0x2445235d,0x2ec92dd8,
0xa6a1a79c,0xaefcb004,0xa4aaa5a5,0xace8adf2,0xa166a35d,0xa9acabbe,0x99e49edf,0xa22fa738,0x1ce913db,0x25281c20,0x2262206b,0x2ab528a4,0x2528242c,0x2d6d2c63,0x271f2623,0x2f822e77,
0xa8a4a954,0xafa8b067,0xa688a7e8,0xad60ae84,0xa38fa528,0xaa37ac3d,0x9c20a0d0,0xa2c6a7e8,0x1edf157f,0x25a51c84,0x2478222f,0x2b592915,0x273825d8,0x2df22ccf,0x28fc284c,0x301d2f16,
0xa9f8aadb,0xb02ab0ca,0xa833a915,0xadd8af16,0xa4dca6a1,0xaac1ac9c,0x9d4da22f,0xa35da84c,0x206b1712,0x26231ce9,0x25bf23f4,0x2bfd2987,0x28a42783,0x2e772d3a,0x2a692987,0x307a2fb5,
0xab4cac31,0xb081b12e,0xa922aa37,0xae51afa8,0xa5f1a80d,0xab4cacfb,0x9e7ba38f,0xa3f4a8a4,0x21661852,0x26a11d4d,0x270524dc,0x2c5029f8,0x29ac2897,0x2efc2da6,0x2bd72ac1,0x30d7302a,
0xac50acf5,0xb0d7b192,0xaa11ab59,0xaec9b01d,0xa705a8ca,0xabd7ad5a,0x9fa8a478,0xa445a8fc,0x2262191b,0x271f1db2,0x282625bf,0x2ca22a69,0x2ab5296d,0x2f822e11,0x2ca22bfd,0x3135307a,
0xacfbadb9,0xb12eb1f7,0xab00ac3d,0xaf42b067,0xa80da987,0xac31adb9,0xa06ba528,0xa491a954,0x235d19e4,0x279c1e16,0x28ca26a1,0x2cf52adb,0x2bbe2a43,0x30042e7d,0x2d5a2c9c,0x319230ca,
0xb185b25c,0xb426b4cc,0xafbbb0b1,0xb1c6b306,0xac76ae18,0xaea3b08a,0xa4dca9ac,0xa738ac37,0x280d1e7b,0x2a0520d0,0x2d472b4c,0x2fdb2d6d,0x30472ee9,0x32663128,0x31f0311b,0x347933a8,
0xb1ddb2c1,0xb453b501,0xb01ab0fb,0xb204b352,0xacbcae77,0xaee9b0ba,0xa528aa05,0xa783ac63,0x284c1edf,0x2a432102,0x2d992bbe,0x30172da6,0x308a2f55,0x32aa315f,0x324f316b,0x34aa33fc,
0xb235b327,0xb481b537,0xb057b145,0xb242b39e,0xad01aed6,0xaf2fb0eb,0xa573aa5d,0xa7cfac90,0x288b1f44,0x2a822134,0x2deb2c18,0x30412ddf,0x30ce2fc2,0x32ef3196,0x32ae31bc,0x34db3428,
0xb28db38e,0xb4afb56d,0xb094b18f,0xb280b3eb,0xad47af36,0xaf75b11b,0xa5bfaab5,0xa80dacbc,0x28ca1fa8,0x2ac12166,0x2e3e2c50,0x306a2e18,0x31113017,0x333531cd,0x330d320e,0x350d3452,
0xb2e5b3f5,0xb4ddb5a3,0xb0d1b1da,0xb2beb41c,0xad8caf95,0xafbbb14b,0xa60aab0d,0xa833ace8,0x29092006,0x2b002199,0x2e902c89,0x30942e51,0x3155304d,0x337a3204,0x336d325f,0x3540347c,
0xb33eb42e,0xb50cb5da,0xb10eb224,0xb2fcb443,0xadd2aff5,0xb001b17c,0xa655ab65,0xa859ad14,0x29482039,0x2b4021cb,0x2ee32cc2,0x30be2e8a,0x31993084,0x33c0323b,0x33cd32b1,0x357234a6,
0xb398b463,0xb53ab612,0xb14bb26f,0xb33bb469,0xae18b02a,0xb024b1ac,0xa6a1abbe,0xa87ead40,0x2987206b,0x2b7f21fd,0x2f362cfb,0x30e72ec3,0x31dd30ba,0x34033273,0x34173303,0x35a534d1,
0xb3f2b497,0xb569b64a,0xb189b2bb,0xb37ab490,0xae5eb05a,0xb047b1dd,0xa6ecac0b,0xa8a4ad6d,0x29c6209d,0x2bbe222f,0x2f882d34,0x31112efc,0x322130f1,0x342632aa,0x34483356,0x35d934fc,
0xb599b682,0xb722b82e,0xb3b9b4b7,0xb4ddb5f9,0xb06ab20e,0xb185b398,0xa8caad99,0xa9f8aefc,0x2bfd2262,0x2cfb23f4,0x313b2f36,0x328d3081,0x344932e2,0x35693453,0x360d3527,0x37bd368b,
0xb5c9b6bb,0xb755b84d,0xb3f8b4df,0xb4feb622,0xb08db23e,0xb1a9b3ca,0xa8f0adc5,0xaa1eaf29,0x2c1e2294,0x2d1b2413,0x31652f6f,0x32b7309d,0x346d331a,0x358e3470,0x36413553,0x37f536ba,
0xb5f9b6f5,0xb789b86d,0xb41cb506,0xb51fb64c,0xb0b1b26f,0xb1cdb3fc,0xa915adf2,0xaa43af55,0x2c3d22c6,0x2d3a242c,0x318f2fa8,0x32e230ba,0x34903352,0x35b3348d,0x3676357e,0x381736e8,
0xb629b72f,0xb7bdb88d,0xb43cb52e,0xb540b676,0xb0d4b2a1,0xb1f0b417,0xa93bae1e,0xaa69af82,0x2c5d22f9,0x2d5a2445,0x31b92fe2,0x330d30d7,0x34b4338b,0x35d934aa,0x36ab35ab,0x38343717,
0xb65ab76a,0xb7f1b8ad,0xb45cb556,0xb561b6a0,0xb0f7b2d2,0xb214b430,0xa961ae4b,0xaa8fafaf,0x2c7d232b,0x2d79245f,0x31e3300e,0x333830f4,0x34d833c3,0x35fe34c7,0x36e035d7,0x38513746,
0xb68bb7a5,0xb813b8ce,0xb47cb57e,0xb582b6ca,0xb11bb303,0xb238b449,0xa987ae77,0xaab5afdb,0x2c9c235d,0x2d992478,0x320e302a,0x33633111,0x34fc33fc,0x362434e4,0x37173604,0x386f3775,
0xb6bdb7e2,0xb82eb8f0,0xb49cb5a7,0xb5a3b6f5,0xb13eb335,0xb25cb463,0xa9acaea3,0xaadbb004,0x2cbc238f,0x2db92491,0x32383047,0x338e312e,0x3520341a,0x364a3501,0x374d3631,0x388d37a5,
0xb6efb80f,0xb849b911,0xb4bdb5d0,0xb5c5b720,0xb162b366,0xb280b47c,0xa9d2aed0,0xab00b01a,0x2cdb23c2,0x2dd824aa,0x32623064,0x33b9314b,0x35453437,0x3670351f,0x3785365e,0x38ab37d6,
0xb865b934,0xb94dba5c,0xb5e7b74c,0xb6fcb85a,0xb2a4b495,0xb3c6b564,0xab26b031,0xac2bb0e4,0x2df824c3,0x2ef6258c,0x33e43168,0x34a13252,0x3697353c,0x37d4362d,0x38ca3803,0x39d038d0,
0xb880b957,0xb96bba84,0xb609b777,0xb720b872,0xb2c8b4af,0xb3ebb57e,0xab4cb047,0xac3db0fb,0x2e1824dc,0x2f1625a5,0x34083185,0x34b7326f,0x36bd355a,0x37fd364c,0x38e9381c,0x39f338eb,
0xb89cb97a,0xb98abaad,0xb62bb7a4,0xb744b88a,0xb2ecb4c9,0xb408b599,0xab72b05d,0xac50b111,0x2e3724f5,0x2f3625bf,0x341e31a2,0x34ce328d,0x36e43577,0x3813366b,0x39093835,0x3a173906,
0xb8b9b99e,0xb9aabad7,0xb64db7d0,0xb768b8a2,0xb310b4e2,0xb41ab5b3,0xab98b074,0xac63b128,0x2e57250f,0x2f5525d8,0x343331c0,0x34e432aa,0x370b3595,0x3828368a,0x3929384e,0x3a3b3922,
0xb8d6b9c3,0xb9cabb02,0xb670b7fd,0xb78cb8ba,0xb335b4fc,0xb42db5ce,0xabbeb08a,0xac76b13e,0x2e772528,0x2f7525f1,0x344931dd,0x34fa32c8,0x373335b3,0x383d36a9,0x39493868,0x3a60393e,
0xb8f3b9e8,0xb9ebbb2d,0xb693b815,0xb7b1b8d2,0xb359b516,0xb43fb5e9,0xabe3b0a1,0xac89b155,0x2e972541,0x2f95260a,0x345f31fa,0x351132e5,0x375b35d2,0x385236c8,0x396a3881,0x3a86395a,
0xb910ba0e,0xba0cbb59,0xb6b6b82c,0xb7d6b8eb,0xb37db530,0xb452b604,0xac05b0b7,0xac9cb16b,0x2eb6255a,0x2fb52623,0x34753217,0x35273303,0x378335f0,0x386836e8,0x398c389b,0x3aac3977,
0xb92eba35,0xba2dbb87,0xb6d9b843,0xb7fbb904,0xb3a2b54a,0xb464b61e,0xac18b0ce,0xacafb182,0x2ed62573,0x2fd5263c,0x348b3235,0x353e3321,0x37ab360e,0x387d3708,0x39ae38b6,0x3ad33994,
0x9ce99db2,0xad3aae11,0x9aad9c20,0xab1aac63,0x9712991b,0xa783a96d,0x8a4893db,0x9aada42c,0x157f10b6,0x25d82102,0x19e41852,0x2a432897,0x1c841b76,0x2ccf2bf0,0x1e161d4d,0x2e7d2da6,
0xa35da445,0xadd8aec9,0xa102a22f,0xabf0ace8,0x9d4d9fa8,0xa833aa11,0x90b699e4,0x9b76a4aa,0x1c201712,0x26882199,0x206b1e7b,0x2b002922,0x22c62199,0x2d602c70,0x249123f4,0x2f422e51,
0xa623a71f,0xae77af82,0xa42ca528,0xac63ad6d,0xa06ba262,0xa8a4aab5,0x93db9ce9,0x9c20a528,0x1edf19e4,0x2738222f,0x235d2166,0x2bbe29ac,0x25a524aa,0x2df22ce8,0x279c26a1,0x30042efc,
0xa84ca8fc,0xaf16b01d,0xa5d8a738,0xaccfadf2,0xa22fa478,0xa915ab59,0x957f9edf,0x9c84a5a5,0x20d01c20,0x27e822c6,0x2528238f,0x2c3d2a37,0x27e82688,0x2e842d60,0x295428a4,0x30672fa8,
0xa987aa69,0xafb5b07a,0xa783a8a4,0xad3aae77,0xa3f4a5bf,0xa987abfd,0x9712a06b,0x9ce9a623,0x222f1d4d,0x284c235d,0x26a124dc,0x2c9c2ac1,0x29152833,0x2f162dd8,0x2adb29f8,0x30ca302a,
0xaac1abd7,0xb02ab0d7,0xa897a9ac,0xada6aefc,0xa4dca705,0xa9f8ac50,0x9852a166,0x9d4da6a1,0x238f1e7b,0x28a423f4,0x280d25f1,0x2cfb2b4c,0x2a372922,0x2fa82e51,0x2c312b4c,0x312e3081,
0xabfdaca2,0xb07ab135,0xa96daab5,0xae11af82,0xa5bfa826,0xaa69aca2,0x991ba262,0x9db2a71f,0x24781fa8,0x28fc2445,0x28ca2705,0x2d5a2bd7,0x2b592a11,0x301d2ec9,0x2cf52c50,0x319230d7,
0xac9cad5a,0xb0cab192,0xaa43abbe,0xae7db004,0xa6a1a8ca,0xaadbacf5,0x99e4a35d,0x9e16a79c,0x2528206b,0x29542491,0x2987280d,0x2db92c31,0x2c3d2b00,0x30672f42,0x2db92cfb,0x31f7312e,
0xb11bb1f0,0xb3a8b479,0xaee9b047,0xb128b266,0xab4cad47,0xad6dafdb,0x9e7ba80d,0xa0d0aa05,0x29ac24dc,0x2c372738,0x2e182c76,0x308a2ea3,0x30b12fbb,0x330631c6,0x325c3185,0x34cc3426,
0xb16bb24f,0xb3fcb4aa,0xaf55b08a,0xb15fb2aa,0xabbead99,0xada6b017,0x9edfa84c,0xa102aa43,0x2a052528,0x2c632783,0x2e772cbc,0x30ba2ee9,0x30fb301a,0x33523204,0x32c131dd,0x35013453,
0xb1bcb2ae,0xb428b4db,0xafc2b0ce,0xb196b2ef,0xac18adeb,0xaddfb041,0x9f44a88b,0xa134aa82,0x2a5d2573,0x2c9027cf,0x2ed62d01,0x30eb2f2f,0x31453057,0x339e3242,0x33273235,0x35373481,
0xb20eb30d,0xb452b50d,0xb017b111,0xb1cdb335,0xac50ae3e,0xae18b06a,0x9fa8a8ca,0xa166aac1,0x2ab525bf,0x2cbc280d,0x2f362d47,0x311b2f75,0x318f3094,0x33eb3280,0x338e328d,0x356d34af,
0xb25fb36d,0xb47cb540,0xb04db155,0xb204b37a,0xac89ae90,0xae51b094,0xa006a909,0xa199ab00,0x2b0d260a,0x2ce82833,0x2f952d8c,0x314b2fbb,0x31da30d1,0x341c32be,0x33f532e5,0x35a334dd,
0xb2b1b3cd,0xb4a6b572,0xb084b199,0xb23bb3c0,0xacc2aee3,0xae8ab0be,0xa039a948,0xa1cbab40,0x2b652655,0x2d142859,0x2ff52dd2,0x317c3001,0x3224310e,0x344332fc,0x342e333e,0x35da350c,
0xb303b417,0xb4d1b5a5,0xb0bab1dd,0xb273b403,0xacfbaf36,0xaec3b0e7,0xa06ba987,0xa1fdab7f,0x2bbe26a1,0x2d40287e,0x302a2e18,0x31ac3024,0x326f314b,0x3469333b,0x34633398,0x3612353a,
0xb356b448,0xb4fcb5d9,0xb0f1b221,0xb2aab426,0xad34af88,0xaefcb111,0xa09da9c6,0xa22fabbe,0x2c0b26ec,0x2d6d28a4,0x305a2e5e,0x31dd3047,0x32bb3189,0x3490337a,0x349733f2,0x364a3569,
0xb527b60d,0xb68bb7bd,0xb2e2b449,0xb453b569,0xaf36b13b,0xb081b28d,0xa262abfd,0xa3f4acfb,0x2d9928ca,0x2efc29f8,0x320e306a,0x33983185,0x34b733b9,0x35f934dd,0x36823599,0x382e3722,
0xb553b641,0xb6bab7f5,0xb31ab46d,0xb470b58e,0xaf6fb165,0xb09db2b7,0xa294ac1e,0xa413ad1b,0x2dc528f0,0x2f292a1e,0x323e308d,0x33ca31a9,0x34df33f8,0x362234fe,0x36bb35c9,0x384d3755,
0xb57eb676,0xb6e8b817,0xb352b490,0xb48db5b3,0xafa8b18f,0xb0bab2e2,0xa2c6ac3d,0xa42cad3a,0x2df22915,0x2f552a43,0x326f30b1,0x33fc31cd,0x3506341c,0x364c351f,0x36f535f9,0x386d3789,
0xb5abb6ab,0xb717b834,0xb38bb4b4,0xb4aab5d9,0xafe2b1b9,0xb0d7b30d,0xa2f9ac5d,0xa445ad5a,0x2e1e293b,0x2f822a69,0x32a130d4,0x341731f0,0x352e343c,0x36763540,0x372f3629,0x388d37bd,
0xb5d7b6e0,0xb746b851,0xb3c3b4d8,0xb4c7b5fe,0xb00eb1e3,0xb0f4b338,0xa32bac7d,0xa45fad79,0x2e4b2961,0x2faf2a8f,0x32d230f7,0x34303214,0x3556345c,0x36a03561,0x376a365a,0x38ad37f1,
0xb604b717,0xb775b86f,0xb3fcb4fc,0xb4e4b624,0xb02ab20e,0xb111b363,0xa35dac9c,0xa478ad99,0x2e772987,0x2fdb2ab5,0x3303311b,0x34493238,0x357e347c,0x36ca3582,0x37a5368b,0x38ce3813,
0xb631b74d,0xb7a5b88d,0xb41ab520,0xb501b64a,0xb047b238,0xb12eb38e,0xa38facbc,0xa491adb9,0x2ea329ac,0x30042adb,0x3335313e,0x3463325c,0x35a7349c,0x36f535a3,0x37e236bd,0x38f0382e,
0xb65eb785,0xb7d6b8ab,0xb437b545,0xb51fb670,0xb064b262,0xb14bb3b9,0xa3c2acdb,0xa4aaadd8,0x2ed029d2,0x301a2b00,0x33663162,0x347c3280,0x35d034bd,0x372035c5,0x380f36ef,0x39113849,
0xb803b8ca,0xb8d0b9d0,0xb53cb697,0xb62db7d4,0xb168b3e4,0xb252b4a1,0xa4c3adf8,0xa58caef6,0x30312b26,0x30e42c2b,0x349532a4,0x356433c6,0x374c35e7,0x385a36fc,0x39343865,0x3a5c394d,
0xb81cb8e9,0xb8ebb9f3,0xb55ab6bd,0xb64cb7fd,0xb185b408,0xb26fb4b7,0xa4dcae18,0xa5a5af16,0x30472b4c,0x30fb2c3d,0x34af32c8,0x357e33eb,0x37773609,0x38723720,0x39573880,0x3a84396b,
0xb835b909,0xb906ba17,0xb577b6e4,0xb66bb813,0xb1a2b41e,0xb28db4ce,0xa4f5ae37,0xa5bfaf36,0x305d2b72,0x31112c50,0x34c932ec,0x35993408,0x37a4362b,0x388a3744,0x397a389c,0x3aad398a,
0xb84eb929,0xb922ba3b,0xb595b70b,0xb68ab828,0xb1c0b433,0xb2aab4e4,0xa50fae57,0xa5d8af55,0x30742b98,0x31282c63,0x34e23310,0x35b3341a,0x37d0364d,0x38a23768,0x399e38b9,0x3ad739aa,
0xb868b949,0xb93eba60,0xb5b3b733,0xb6a9b83d,0xb1ddb449,0xb2c8b4fa,0xa528ae77,0xa5f1af75,0x308a2bbe,0x313e2c76,0x34fc3335,0x35ce342d,0x37fd3670,0x38ba378c,0x39c338d6,0x3b0239ca,
0xb881b96a,0xb95aba86,0xb5d2b75b,0xb6c8b852,0xb1fab45f,0xb2e5b511,0xa541ae97,0xa60aaf95,0x30a12be3,0x31552c89,0x35163359,0x35e9343f,0x38153693,0x38d237b1,0x39e838f3,0x3b2d39eb,
0xb89bb98c,0xb977baac,0xb5f0b783,0xb6e8b868,0xb217b475,0xb303b527,0xa55aaeb6,0xa623afb5,0x30b72c05,0x316b2c9c,0x3530337d,0x36043452,0x382c36b6,0x38eb37d6,0x3a0e3910,0x3b593a0c,
0xb8b6b9ae,0xb994bad3,0xb60eb7ab,0xb708b87d,0xb235b48b,0xb321b53e,0xa573aed6,0xa63cafd5,0x30ce2c18,0x31822caf,0x354a33a2,0x361e3464,0x384336d9,0x390437fb,0x3a35392e,0x3b873a2d,
0x214d2216,0x319b326c,0x1f762084,0x2fe830c8,0x1c521de4,0x2c962e40,0x14b6197f,0x250229d7,0x97db8e48,0xa82c9ead,0x9d1b9b12,0xad6bab82,0xa0209ead,0xb05eaf14,0xa1b2a0e9,0xb204b131,
0x27f32890,0x3241332b,0x259826c6,0x306a3156,0x227b246b,0x2d202efb,0x1b122020,0x25982a87,0x9de494b6,0xa8aa9f76,0xa3a8a14d,0xae0eac32,0xa62fa502,0xb0e1afe8,0xa845a75d,0xb2b6b1cc,
0x2aa02b9b,0x32e733e8,0x28aa29a5,0x30e131e5,0x2566275d,0x2daa2fb6,0x1de422df,0x262f2b36,0xa0e997db,0xa927a020,0xa661a46b,0xaeb0aca2,0xa927a82c,0xb163b05e,0xab1daa22,0xb368b266,
0x2ca22d52,0x338d3452,0x2a872be6,0x31563273,0x278f2927,0x2e333039,0x202024cf,0x26c62be6,0xa2df997f,0xa9a5a084,0xa877a62f,0xaf53ad13,0xab36a9d7,0xb1e5b0c8,0xacfaac4b,0xb40cb300,
0x2df52ed6,0x341834b0,0x2c322d13,0x31cc3300,0x28dc2aa0,0x2ebd3096,0x214d262f,0x275d2c4b,0xa46b9b12,0xaa22a0e9,0xa9bea7f3,0xaff5ad84,0xaca2ab82,0xb266b131,0xae65ad84,0xb464b399,
0x2f46302c,0x346a350c,0x2d202e33,0x3241338d,0x29f02c0c,0x2f4630f3,0x227b278f,0x27f32ca2,0xa5669c52,0xaaa0a14d,0xab04a8dc,0xb04badf5,0xadaaac96,0xb2e7b19b,0xafcfaebd,0xb4bcb418,
0x304b30ed,0x34bc3568,0x2e0e2f53,0x32b6340c,0x2b042cc8,0x2fcf3150,0x23a82877,0x28452cfa,0xa6619d1b,0xab1da1b2,0xac25a9be,0xb09cae65,0xaeb0ad6b,0xb368b204,0xb09caff5,0xb512b464,
0x30f331ad,0x350c35c4,0x2efb3039,0x332b3452,0x2c0c2d84,0x302c31ad,0x246b2927,0x28902d52,0xa75d9de4,0xab9ba216,0xacc8aaa0,0xb0edaed6,0xafb6ae40,0xb3e8b26c,0xb150b096,0xb568b4b0,
0x355d361e,0x37c63867,0x339f3497,0x359836b4,0x3071320a,0x32913473,0x28dc2daa,0x2b363032,0xac0ca27b,0xae01a4cf,0xb13eaf46,0xb3bdb163,0xb434b2d5,0xb627b506,0xb5beb4fa,0xb826b73e,
0x35ac3678,0x3808388f,0x340934dd,0x35cf36f5,0x30b53266,0x32d534a0,0x29272e01,0x2b82305e,0xac4ba2df,0xae40a502,0xb18eafb6,0xb406b19b,0xb473b33d,0xb663b539,0xb612b545,0xb84cb784,
0x35fb36d0,0x382c38b7,0x34433521,0x36073736,0x30f932c2,0x331834ce,0x29722e59,0x2bcd308a,0xac89a344,0xae7ea534,0xb1dfb013,0xb42eb1d2,0xb4b3b3a5,0xb6a0b56b,0xb666b58f,0xb872b7c9,
0x36493728,0x385038de,0x347c3565,0x363e3776,0x313e331e,0x335c34fa,0x29be2eb0,0x2c0c30b5,0xacc8a3a8,0xaebda566,0xb22fb04b,0xb455b20a,0xb4f1b406,0xb6dcb59d,0xb6b9b5d8,0xb898b807,
0x3697377e,0x38743904,0x34b635a9,0x367537b6,0x3182337a,0x339f3527,0x2a092f08,0x2c3230e1,0xad07a406,0xaefba598,0xb27fb083,0xb47cb241,0xb530b43a,0xb717b5cf,0xb70cb621,0xb8bdb828,
0x36e437d4,0x3897392a,0x34ee35ed,0x36ab37f5,0x31c633d6,0x33e23554,0x2a542f5f,0x2c57310c,0xad45a439,0xaf3aa5cb,0xb2cfb0bb,0xb4a4b279,0xb56eb46d,0xb752b601,0xb75db669,0xb8e1b84a,
0x37303814,0x38b9394e,0x3527362f,0x36e1381a,0x320a3418,0x34123580,0x2aa02fb6,0x2c7d3137,0xad84a46b,0xaf78a5fd,0xb31eb0f3,0xb4cbb2b0,0xb5acb4a0,0xb78cb632,0xb7adb6b1,0xb905b86b,
0x377c383e,0x38db3972,0x355f3672,0x37173838,0x324e3446,0x343435ac,0x2aeb3007,0x2ca23163,0xadc3a49d,0xafb6a62f,0xb36eb12b,0xb4f1b2e7,0xb5eab4d4,0xb7c6b663,0xb7fdb6f8,0xb928b88b,
0x38fd3996,0x39f33a91,0x374c3857,0x3874393e,0x345535d8,0x355d3730,0x2cc8318e,0x2df532e7,0xaff5a661,0xb0f3a7f3,0xb518b31e,0xb649b46a,0xb800b694,0xb8dbb808,0xb94bb8ab,0xba45b99b,
0x391e39b8,0x3a0f3aad,0x37813875,0x388c3959,0x34763604,0x357d375a,0x2cee31b9,0x2e1a3312,0xb01aa694,0xb112a813,0xb53fb356,0xb66fb485,0xb81cb6c5,0xb8f5b81f,0xb96db8cb,0xba61b9b7,
0x393e39da,0x3a2b3ac7,0x37b63893,0x38a53974,0x3497362f,0x359d3784,0x2d1331e5,0x2e40333d,0xb039a6c6,0xb131a82c,0xb565b38d,0xb694b4a0,0xb838b6f5,0xb90fb836,0xb98eb8ea,0xba7cb9d2,
0x395e39fb,0x3a453ae0,0x37ea38b0,0x38bd398e,0x34b9365b,0x35be37ad,0x2d393210,0x2e653368,0xb058a6f8,0xb150a845,0xb58cb3c3,0xb6b9b4bc,0xb854b725,0xb928b84c,0xb9aeb909,0xba97b9ed,
0x397d3a1b,0x3a5f3af9,0x380f38cd,0x38d539a8,0x34da3686,0x35de37d7,0x2d5e323b,0x2e8b3393,0xb077a72a,0xb16fa85e,0xb5b2b3fa,0xb6deb4d7,0xb870b755,0xb941b863,0xb9ceb927,0xbab0ba07,
0x399b3a3a,0x3a793b10,0x382838ea,0x38ed39c1,0x34fa36b1,0x35fe3800,0x2d843266,0x2eb033bd,0xb096a75d,0xb18ea877,0xb5d8b418,0xb703b4f1,0xb88bb784,0xb95ab879,0xb9edb945,0xbac9ba21,
0x39b93a58,0x3a913b26,0x38423906,0x390439da,0x351b36dc,0x361e3814,0x2daa3291,0x2ed633e8,0xb0b5a78f,0xb1ada890,0xb5feb434,0xb728b50c,0xb8a6b7b3,0xb972b88f,0xba0bb962,0xbae0ba3a,
0x39d73a75,0x3aa93b3c,0x385b3922,0x391b39f2,0x353c3706,0x363e3828,0x2dcf32bc,0x2efb3409,0xb0d4a7c1,0xb1cca8aa,0xb624b44f,0xb74cb527,0xb8c1b7e2,0xb98ab8a5,0xba29b97f,0xbaf7ba52,
0x3ac03b50,0x3b5e3bcb,0x39323a0a,0x39de3ab8,0x365e383c,0x375738d7,0x2f21341f,0x302634c8,0xb1eba8c3,0xb2e1a98c,0xb770b542,0xb846b615,0xb9a2b8bb,0xba51b960,0xbb0dba6a,0xbb9cbb11,
0x3ad73b63,0x3b6e3bd6,0x39493a22,0x39f23acb,0x367d3850,0x377638ea,0x2f463434,0x303934dd,0xb20aa8dc,0xb300a9a5,0xb795b55d,0xb857b62f,0xb9b9b8d0,0xba65b974,0xbb22ba81,0xbba9bb24,
0x3aec3b75,0x3b7d3bdf,0x395f3a39,0x3a063ade,0x369d3864,0x379538fd,0x2f6c3449,0x304b34f1,0xb229a8f5,0xb31ea9be,0xb7b8b577,0xb868b649,0xb9d0b8e5,0xba79b987,0xbb36ba97,0xbbb6bb35,
0x3b013b86,0x3b8c3be7,0x39753a4f,0x3a193af0,0x36bc3878,0x37b3390f,0x2f91345e,0x305e3506,0xb247a90e,0xb33da9d7,0xb7dcb592,0xb879b663,0xb9e7b8fa,0xba8cb99a,0xbb4abaad,0xbbc2bb46,
0x3b153b96,0x3b993bee,0x398a3a65,0x3a2d3b02,0x36dc388b,0x37d13921,0x2fb63473,0x3071351b,0xb266a927,0xb35ca9f0,0xb800b5ac,0xb88ab67d,0xb9fdb90f,0xba9fb9ad,0xbb5cbac3,0xbbccbb56,
0x3b283ba5,0x3ba63bf4,0x39a03a7a,0x3a3f3b13,0x36fb389e,0x37ef3933,0x2fdc3488,0x30833530,0xb285a940,0xb37aaa09,0xb811b5c7,0xb89bb697,0xba12b924,0xbab1b9c0,0xbb6dbad7,0xbbd6bb65,
0x3b3b3bb3,0x3bb23bf9,0x39b53a8f,0x3a523b24,0x371a38b2,0x38073945,0x3001349d,0x30963545,0xb2a4a959,0xb399aa22,0xb823b5e1,0xb8abb6b1,0xba28b938,0xbac3b9d2,0xbb7ebaeb,0xbbdfbb74,
0x3b4d3bc0,0x3bbd3bfc,0x39ca3aa4,0x3a643b34,0x373938c5,0x38153957,0x301334b3,0x30a9355a,0xb2c2a972,0xb3b7aa3b,0xb834b5fb,0xb8bcb6ca,0xba3cb94c,0xbad4b9e4,0xbb8dbaff,0xbbe6bb82,
0x20e921b2,0x31313204,0x1ead2020,0x2f14305e,0x1b121d1b,0x2b822d6b,0xe4817db,0x1ead282c,0x997f94b6,0xa9d7a502,0x9de49c52,0xae40ac96,0xa0849f76,0xb0c8afe8,0xa216a14d,0xb26cb19b,
0x275d2845,0x31cc32b6,0x2502262f,0x2fe830e1,0x214d23a8,0x2c322e0e,0x14b61de4,0x1f7628aa,0xa0209b12,0xaa87a598,0xa46ba27b,0xaefbad20,0xa6c6a598,0xb156b06a,0xa890a7f3,0xb32bb241,
0x2a222b1d,0x32663368,0x282c2927,0x305e3163,0x246b2661,0x2ca22eb0,0x17db20e9,0x20202927,0xa2df9de4,0xab36a62f,0xa75da566,0xafb6adaa,0xa9a5a8aa,0xb1e5b0e1,0xab9baaa0,0xb3e8b2e7,
0x2c4b2cfa,0x3300340c,0x29d72b36,0x30c831e5,0x262f2877,0x2d132f53,0x197f22df,0x208429a5,0xa4cfa020,0xabe6a6c6,0xa927a78f,0xb039ae33,0xabe6aa87,0xb273b156,0xad52aca2,0xb452b38d,
0x2d842e65,0x33993464,0x2b822ca2,0x31313266,0x27f329be,0x2d842ff5,0x1b12246b,0x20e92a22,0xa62fa14d,0xac4ba75d,0xaaa0a8dc,0xb096aebd,0xad13ac32,0xb300b1cc,0xaed6adf5,0xb4b0b418,
0x2ebd2fcf,0x341834bc,0x2c962daa,0x319b32e7,0x28dc2b04,0x2df5304b,0x1c522566,0x214d2aa0,0xa78fa27b,0xaca2a7f3,0xac0ca9f0,0xb0f3af46,0xae33ad20,0xb38db241,0xb02caf46,0xb50cb46a,
0x2ff5309c,0x34643512,0x2d6b2eb0,0x32043368,0x29be2c25,0x2e65309c,0x1d1b2661,0x21b22b1d,0xa877a3a8,0xacfaa845,0xacc8ab04,0xb150afcf,0xaf53ae0e,0xb40cb2b6,0xb0edb04b,0xb568b4bc,
0x30963150,0x34b03568,0x2e402fb6,0x326c33e8,0x2aa02cc8,0x2ed630ed,0x1de4275d,0x22162b9b,0xa927a46b,0xad52a890,0xad84ac0c,0xb1adb02c,0xb039aefb,0xb452b32b,0xb1adb0f3,0xb5c4b50c,
0x34fa35be,0x373e3826,0x32d53434,0x35063627,0x2f46313e,0x316333bd,0x227b2c0c,0x24cf2e01,0xadaaa8dc,0xb032ab36,0xb20ab071,0xb473b291,0xb497b39f,0xb6b4b598,0xb61eb55d,0xb867b7c6,
0x35453612,0x3784384c,0x333d3473,0x35393663,0x2fb6318e,0x319b3406,0x22df2c4b,0x25022e40,0xae01a927,0xb05eab82,0xb266b0b5,0xb4a0b2d5,0xb4ddb409,0xb6f5b5cf,0xb678b5ac,0xb88fb808,
0x358f3666,0x37c93872,0x33a534b3,0x356b36a0,0x301331df,0x31d2342e,0x23442c89,0x25342e7e,0xae59a972,0xb08aabcd,0xb2c2b0f9,0xb4ceb318,0xb521b443,0xb736b607,0xb6d0b5fb,0xb8b7b82c,
0x35d836b9,0x38073898,0x340634f1,0x359d36dc,0x304b322f,0x320a3455,0x23a82cc8,0x25662ebd,0xaeb0a9be,0xb0b5ac0c,0xb31eb13e,0xb4fab35c,0xb565b47c,0xb776b63e,0xb728b649,0xb8deb850,
0x3621370c,0x382838bd,0x343a3530,0x35cf3717,0x3083327f,0x3241347c,0x24062d07,0x25982efb,0xaf08aa09,0xb0e1ac32,0xb37ab182,0xb527b39f,0xb5a9b4b6,0xb7b6b675,0xb77eb697,0xb904b874,
0x3669375d,0x384a38e1,0x346d356e,0x36013752,0x30bb32cf,0x327934a4,0x24392d45,0x25cb2f3a,0xaf5faa54,0xb10cac57,0xb3d6b1c6,0xb554b3e2,0xb5edb4ee,0xb7f5b6ab,0xb7d4b6e4,0xb92ab897,
0x36b137ad,0x386b3905,0x34a035ac,0x3632378c,0x30f3331e,0x32b034cb,0x246b2d84,0x25fd2f78,0xafb6aaa0,0xb137ac7d,0xb418b20a,0xb580b412,0xb62fb527,0xb81ab6e1,0xb814b730,0xb94eb8b9,
0x36f837fd,0x388b3928,0x34d435ea,0x366337c6,0x312b336e,0x32e734f1,0x249d2dc3,0x262f2fb6,0xb007aaeb,0xb163aca2,0xb446b24e,0xb5acb434,0xb672b55f,0xb838b717,0xb83eb77c,0xb972b8db,
0x38ab394b,0x399b3a45,0x36943800,0x380838db,0x331e3518,0x346a3649,0x26612ff5,0x27f330f3,0xb18eacc8,0xb2e7adf5,0xb5d8b455,0xb730b55d,0xb857b74c,0xb93eb874,0xb996b8fd,0xba91b9f3,
0x38cb396d,0x39b73a61,0x36c5381c,0x381f38f5,0x3356353f,0x3485366f,0x2694301a,0x28133112,0xb1b9acee,0xb312ae1a,0xb604b476,0xb75ab57d,0xb875b781,0xb959b88c,0xb9b8b91e,0xbaadba0f,
0x38ea398e,0x39d23a7c,0x36f53838,0x3836390f,0x338d3565,0x34a03694,0x26c63039,0x282c3131,0xb1e5ad13,0xb33dae40,0xb62fb497,0xb784b59d,0xb893b7b6,0xb974b8a5,0xb9dab93e,0xbac7ba2b,
0x390939ae,0x39ed3a97,0x37253854,0x384c3928,0x33c3358c,0x34bc36b9,0x26f83058,0x28453150,0xb210ad39,0xb368ae65,0xb65bb4b9,0xb7adb5be,0xb8b0b7ea,0xb98eb8bd,0xb9fbb95e,0xbae0ba45,
0x392739ce,0x3a073ab0,0x37553870,0x38633941,0x33fa35b2,0x34d736de,0x272a3077,0x285e316f,0xb23bad5e,0xb393ae8b,0xb686b4da,0xb7d7b5de,0xb8cdb80f,0xb9a8b8d5,0xba1bb97d,0xbaf9ba5f,
0x394539ed,0x3a213ac9,0x3784388b,0x3879395a,0x341835d8,0x34f13703,0x275d3096,0x2877318e,0xb266ad84,0xb3bdaeb0,0xb6b1b4fa,0xb800b5fe,0xb8eab828,0xb9c1b8ed,0xba3ab99b,0xbb10ba79,
0x39623a0b,0x3a3a3ae0,0x37b338a6,0x388f3972,0x343435fe,0x350c3728,0x278f30b5,0x289031ad,0xb291adaa,0xb3e8aed6,0xb6dcb51b,0xb814b61e,0xb906b842,0xb9dab904,0xba58b9b9,0xbb26ba91,
0x397f3a29,0x3a523af7,0x37e238c1,0x38a5398a,0x344f3624,0x3527374c,0x27c130d4,0x28aa31cc,0xb2bcadcf,0xb409aefb,0xb706b53c,0xb828b63e,0xb922b85b,0xb9f2b91b,0xba75b9d7,0xbb3cbaa9,
0x3a6a3b0d,0x3b113b9c,0x38bb39a2,0x39603a51,0x35423770,0x36153846,0x28c331eb,0x298c32e1,0xb41faf21,0xb4c8b026,0xb83cb65e,0xb8d7b757,0xba0ab932,0xbab8b9de,0xbb50bac0,0xbbcbbb5e,
0x3a813b22,0x3b243ba9,0x38d039b9,0x39743a65,0x355d3795,0x362f3857,0x28dc320a,0x29a53300,0xb434af46,0xb4ddb039,0xb850b67d,0xb8eab776,0xba22b949,0xbacbb9f2,0xbb63bad7,0xbbd6bb6e,
0x3a973b36,0x3b353bb6,0x38e539d0,0x39873a79,0x357737b8,0x36493868,0x28f53229,0x29be331e,0xb449af6c,0xb4f1b04b,0xb864b69d,0xb8fdb795,0xba39b95f,0xbadeba06,0xbb75baec,0xbbdfbb7d,
0x3aad3b4a,0x3b463bc2,0x38fa39e7,0x399a3a8c,0x359237dc,0x36633879,0x290e3247,0x29d7333d,0xb45eaf91,0xb506b05e,0xb878b6bc,0xb90fb7b3,0xba4fb975,0xbaf0ba19,0xbb86bb01,0xbbe7bb8c,
0x3ac33b5c,0x3b563bcc,0x390f39fd,0x39ad3a9f,0x35ac3800,0x367d388a,0x29273266,0x29f0335c,0xb473afb6,0xb51bb071,0xb88bb6dc,0xb921b7d1,0xba65b98a,0xbb02ba2d,0xbb96bb15,0xbbeebb99,
0x3ad73b6d,0x3b653bd6,0x39243a12,0x39c03ab1,0x35c73811,0x3697389b,0x29403285,0x2a09337a,0xb488afdc,0xb530b083,0xb89eb6fb,0xb933b7ef,0xba7ab9a0,0xbb13ba3f,0xbba5bb28,0xbbf4bba6,
0x3aeb3b7e,0x3b743bdf,0x39383a28,0x39d23ac3,0x35e13823,0x36b138ab,0x295932a4,0x2a223399,0xb49db001,0xb545b096,0xb8b2b71a,0xb945b807,0xba8fb9b5,0xbb24ba52,0xbbb3bb3b,0xbbf9bbb2,
0x3aff3b8d,0x3b823be6,0x394c3a3c,0x39e43ad4,0x35fb3834,0x36ca38bc,0x297232c2,0x2a3b33b7,0xb4b3b013,0xb55ab0a9,0xb8c5b739,0xb957b815,0xbaa4b9ca,0xbb34ba64,0xbbc0bb4d,0xbbfcbbbd,
0x39b839ba,0x3a973ab5,0x39b339b5,0x3a583a78,0x39af39b1,0x3a153a37,0x39aa39ad,0x39cd39f2,0x39a639a8,0x398239a8,0x39a139a4,0x3933395b,0x399d399f,0x38e03909,0x3999399b,0x388938b5,
0xb979b972,0xb865b832,0xb986b980,0xb8c7b896,0xb994b98d,0xb924b8f6,0xb9a1b99b,0xb97db951,0xb9afb9a8,0xb9d2b9a8,0xb9bcb9b5,0xba21b9fa,0xb9c9b9c3,0xba6bba47,0xb9d6b9d0,0xbab0ba8e,
0xb9f4b9fe,0xbac7bae9,0xb9dfb9e9,0xba7ebaa3,0xb9c9b9d4,0xba2dba56,0xb9b3b9be,0xb9d6ba02,0xb99db9a8,0xb979b9a8,0xb986b992,0xb916b948,0xb970b97b,0xb8adb8e2,0xb958b964,0xb840b877,
0x39373927,0x381a37b7,0x39583948,0x38943858,0x39793969,0x390738ce,0x39993989,0x3974393e,0x39b839a8,0x39da39a8,0x39d639c7,0x3a393a0b,0x39f439e5,0x3a903a65,0x3a113a02,0x3ade3ab8,
0x3a2d3a3f,0x3af43b1a,0x3a093a1b,0x3aa23acc,0x39e339f6,0x3a453a74,0x39bc39d0,0x39df3a13,0x399439a8,0x397039a8,0x396b3980,0x38f83935,0x39413956,0x387a38ba,0x3916392b,0x37e83838,
0xb8f3b8d8,0xb79bb705,0xb929b90e,0xb85fb817,0xb95db943,0xb8eab8a6,0xb990b976,0xb96bb92b,0xb9c0b9a8,0xb9e3b9a8,0xb9f0b9d8,0xba50ba1b,0xba1dba07,0xbab3ba83,0xba49ba33,0xbb0abae0,
0xba64ba7c,0xbb1ebb46,0xba31ba4b,0xbac4baf3,0xb9fcba17,0xba5cba92,0xb9c5b9e1,0xb9e7ba23,0xb98bb9a8,0xb966b9a8,0xb94fb96d,0xb8dbb922,0xb911b930,0xb845b891,0xb8d1b8f1,0xb74eb7ee,
0x38ad3887,0x36ff364e,0x38f838d3,0x382a37ac,0x3941391d,0x38cc387c,0x39863964,0x39623918,0x39c939a8,0x39eb39a8,0x3a0939e9,0x3a673a2b,0x3a453a27,0x3ad53aa0,0x3a7e3a62,0x3b323b05,
0x3b453b6e,0x3bbc3bdd,0x3ae53b17,0x3b573b8f,0x3a733aae,0x3ac73b14,0x39f03a33,0x3a113a71,0x395d39a8,0x393739a8,0x38bc390e,0x384038bf,0x380f3867,0x365f3775,0x36af376a,0x341a3540,
0xb65fb593,0xb389b115,0xb7e8b726,0xb625b4f9,0xb8adb852,0xb830b748,0xb958b905,0xb933b8b5,0xb9f4b9a8,0xba15b9a8,0xba7eba3b,0xbad1ba78,0xbaf4babc,0xbb63bb20,0xbb57bb28,0xbbc6bb9b,
0xbb68bb91,0xbbd0bbed,0xbb04bb39,0xbb6fbba6,0xba89bac9,0xbadbbb2b,0xb9f8ba43,0xba19ba7f,0xb954b9a8,0xb92eb9a8,0xb89eb8fb,0xb820b8ab,0xb7b2b83d,0xb5ebb71b,0xb60eb6e3,0xb2deb4b1,
0x35bc34d5,0x32322f0e,0x377a369e,0x35b13469,0x388e3828,0x380f36ee,0x394f38f1,0x392938a0,0x39fc39a8,0x3a1d39a8,0x3a933a4b,0x3ae53a87,0x3b133ad6,0x3b7a3b36,0x3b783b49,0x3bd93bb1,
0x3b873baf,0x3be13bf8,0x3b213b58,0x3b853bbb,0x3a9e3ae3,0x3aee3b41,0x3a003a52,0x3a213a8e,0x394a39a8,0x392439a8,0x387f38e7,0x37fe3896,0x37423812,0x357636c1,0x356a3659,0x31853420,
0xb517b414,0xb0d7abd9,0xb70ab614,0xb53ab3ae,0xb86fb7f9,0xb7ddb693,0xb946b8dd,0xb91fb88c,0xba04b9a8,0xba25b9a8,0xbaa9ba5a,0xbaf7ba95,0xbb2fbaf0,0xbb90bb4b,0xbb96bb67,0xbbe8bbc4,
0xbba3bbc9,0xbbefbbff,0xbb3dbb74,0xbb9abbcd,0xbab3bafc,0xbb01bb55,0xba09ba62,0xba29ba9c,0xb941b9a8,0xb91bb9a8,0xb85fb8d3,0xb7bdb881,0xb6d2b7cd,0xb4ffb665,0xb4c3b5ce,0xb029b31b,
0x346f32a1,0x2ef52248,0x36993587,0x34c33288,0x385037a1,0x379b3637,0x393c38c9,0x39163877,0x3a0d39a8,0x3a2d39a8,0x3abd3a69,0x3b0a3aa3,0x3b4a3b08,0x3ba33b5f,0x3bb03b82,0x3bf43bd5,
0x3bf83c00,0x3bf93bd4,0x3bac3bdc,0x3be43bfe,0x3b133b69,0x3b543bab,0x3a313aaa,0x3a503ae0,0x391139a8,0x38ea39a8,0x377a386d,0x366b3817,0x34873608,0x313b348d,0x2d9731f4,0xad65291b,
0xac3828b6,0x2ec33365,0xb44bb160,0xb0bea57f,0xb759b5da,0xb648b45d,0xb90cb862,0xb8e5b80d,0xba35b9a8,0xba54b9a8,0xbb1bbab1,0xbb5cbae6,0xbbb5bb72,0xbbe9bbb2,0xbbfcbbe3,0xbbf5bc00,
0xbbfebbfc,0xbbefbbbc,0xbbbdbbe9,0xbbeebc00,0xbb24bb7b,0xbb63bbb9,0xba39bab8,0xba58baed,0xb907b9a8,0xb8e0b9a8,0xb737b858,0xb625b802,0xb40eb5ab,0xb042b42c,0xa9b1b0cb,0x30109a48,
0x25e4ad7e,0xb0beb475,0x33a23036,0x2f8ba3db,0x3715357c,0x360233f7,0x3902384d,0x38db37ee,0x3a3d39a8,0x3a5c39a8,0x3b2c3abf,0x3b6a3af3,0x3bc53b84,0x3bf23bc0,0x3bff3bee,0x3be93c00,
0x3c003bf4,0x3be23ba0,0x3bcc3bf3,0x3bf53bff,0x3b353b8c,0x3b713bc6,0x3a413ac6,0x3a603af9,0x38fd39a8,0x38d639a8,0x36f43842,0x35df37d8,0x3328354c,0x2e913396,0x16482f40,0xb16ca852,
0x251b304e,0x32193534,0xb2adae14,0xad972aac,0xb6d2b51d,0xb5bcb334,0xb8f8b838,0xb8d1b7c2,0xba45b9a8,0xba64b9a8,0xbb3dbacc,0xbb78baff,0xbbd3bb95,0xbbf8bbcb,0xbc00bbf7,0xbbdabbfd,
0xbbfebbe6,0xbbd2bb80,0xbbd9bbfa,0xbbfbbbfb,0xbb45bb9d,0xbb7fbbd1,0xba49bad3,0xba67bb05,0xb8f3b9a8,0xb8ccb9a8,0xb6afb82d,0xb599b7ac,0xb232b4ed,0xac9cb2d2,0x294dace7,0x32c62c83,
0xac06b1db,0xb371b5f1,0x31b62b75,0x2b43adb0,0x368d34bd,0x3576326f,0x38ee3822,0x38c73796,0x3a4d39a8,0x3a6b39a8,0x3b4c3ad9,0x3b853b0b,0x3bdf3ba4,0x3bfd3bd6,0x3bfc3bfd,0x3bc83bf8,
0x3bbd3b5a,0x3b473a99,0x3bfe3bf4,0x3bf93bbe,0x3b8b3bdb,0x3bb83bf7,0x3a6f3b11,0x3a8c3b3e,0x38c139a8,0x389939a8,0x35523780,0x343236cc,0x294d320d,0xad332de2,0xb40eaedc,0xb6a4b408,
0x346336aa,0x36f438b0,0xa6ad3004,0x2e2d3451,0xb52fb1aa,0xb40ead1a,0xb8bcb76a,0xb894b6b5,0xba73b9a8,0xba90b9a8,0xbb92bb17,0xbbbdbb43,0xbbffbbe0,0xbbf6bbf9,0xbbb2bbf0,0xbb35bbb4,
0xbba5bb30,0xbb21ba5e,0xbc00bbeb,0xbbf3bbaa,0xbb98bbe4,0xbbc2bbfb,0xba76bb1d,0xba93bb49,0xb8b7b9a8,0xb88eb9a8,0xb50bb753,0xb3d3b69e,0xa17fb147,0x2f27ac51,0x34b73099,0x37423499,
0xb50bb75e,0xb790b900,0x9cb6b12e,0xb010b4e1,0x34e730e4,0x33892b11,0x38b2373d,0x38893687,0x3a7a39a8,0x3a9739a8,0x3b9e3b22,0x3bc63b4e,0x3c003be8,0x3bef3bfd,0x3b983be5,0x3b0d3b9e,
0x3b893b02,0x3af73a1f,0x3c003bdf,0x3beb3b93,0x3ba33bec,0x3bcb3bfe,0x3a7e3b28,0x3a9b3b53,0x38ad39a8,0x388439a8,0x34c33726,0x33403670,0xa51b3080,0xb08d297f,0xb55eb1c3,0xb7ddb529,
0x35b13807,0x3815394d,0x28843257,0x31093570,0xb49fb01d,0xb2f7a7da,0xb8a8b710,0xb87fb659,0xba81b9a8,0xba9eb9a8,0xbba9bb2e,0xbbcfbb58,0xbbffbbef,0xbbe6bbff,0xbb7abbd7,0xbae1bb86,
0xbb6abad0,0xbacbb9dc,0xbbfdbbd0,0xbbe1bb79,0xbbaebbf2,0xbbd3bc00,0xba85bb33,0xbaa2bb5d,0xb8a3b9a8,0xb87ab9a8,0xb47bb6f9,0xb2adb642,0x2a7aaf72,0x3185a4b6,0x360232ea,0x383a35b6,
0xb654b85d,0xb85fb996,0xac38b37d,0xb201b5fd,0x34572eaa,0x32631e48,0x389e36e3,0x3874362b,0x3a8939a8,0x3aa539a8,0x3bb33b39,0x3bd73b62,0x3bfc3bf5,0x3bdc3c00,0x3b593bc7,0x3ab33b6b,
0x39b739b9,0x3a883aa6,0x39b239b4,0x3a483a68,0x39ae39b0,0x3a033a26,0x39a939ab,0x39bb39e0,0x39a539a7,0x396e3995,0x39a039a3,0x391e3947,0x399c399e,0x38ca38f5,0x3997399a,0x3873389f,
0xb97cb975,0xb87eb84c,0xb98ab983,0xb8deb8ae,0xb997b991,0xb93bb90d,0xb9a5b99e,0xb993b967,0xb9b2b9ab,0xb9e6b9bd,0xb9bfb9b9,0xba34ba0e,0xb9ccb9c6,0xba7dba59,0xb9d9b9d3,0xbac0ba9f,
0xb9efb9f9,0xbab6bad9,0xb9d9b9e4,0xba6aba91,0xb9c4b9cf,0xba18ba42,0xb9aeb9b9,0xb9bfb9ec,0xb997b9a3,0xb961b991,0xb981b98c,0xb8fcb92f,0xb96ab975,0xb892b8c8,0xb953b95e,0xb824b85c,
0x3940392f,0x383937f6,0x39613950,0x38b13876,0x39813971,0x392338eb,0x39a03991,0x398e395a,0x39bf39b0,0x39f339c1,0x39de39cf,0x3a4f3a22,0x39fb39ec,0x3aa43a7b,0x3a183a0a,0x3af03acb,
0x3a243a36,0x3ae13b07,0x39ff3a12,0x3a8b3ab7,0x39d939ec,0x3a2c3a5d,0x39b239c6,0x39c439f9,0x398a399e,0x3953398c,0x39613975,0x38d93917,0x3936394b,0x3859389a,0x390b3921,0x37a43816,
0xb901b8e6,0xb7e6b750,0xb936b91c,0xb883b83c,0xb96ab950,0xb90bb8c8,0xb99cb983,0xb98ab94b,0xb9ccb9b4,0xb9ffb9c6,0xb9fbb9e4,0xba6aba36,0xba28ba12,0xbacaba9b,0xba53ba3e,0xbb1dbaf5,
0xba57ba70,0xbb09bb33,0xba24ba3e,0xbaabbadc,0xb9efba0a,0xba40ba77,0xb9b7b9d3,0xb9c8ba05,0xb97cb99a,0xb944b988,0xb940b95e,0xb8b6b8fe,0xb901b921,0xb81eb86b,0xb8c0b8e1,0xb6fcb79e,
0x38c0389a,0x375636a7,0x390b38e6,0x38543800,0x3953392f,0x38f238a4,0x39973975,0x3985393d,0x39d939b9,0x3a0c39ca,0x3a1839f9,0x3a843a4a,0x3a533a36,0x3aed3abb,0x3a8b3a70,0x3b473b1c,
0x3b2e3b5a,0x3ba63bce,0x3aca3afe,0x3b373b74,0x3a533a91,0x3a9d3aef,0x39cc3a12,0x39de3a42,0x39363983,0x38fc3971,0x389238e6,0x37fb3880,0x37c5383c,0x35d136eb,0x3651370d,0x330934ae,
0xb6c3b5fa,0xb460b251,0xb824b788,0xb6b8b590,0xb8d9b880,0xb873b7d5,0xb981b92f,0xb96eb8f5,0xba18b9cf,0xba48b9e0,0xba9dba5d,0xbafabaa6,0xbb0fbad9,0xbb80bb43,0xbb6cbb40,0xbbd8bbb2,
0xbb51bb7d,0xbbbdbbe0,0xbae7bb1f,0xbb4ebb8c,0xba66baa9,0xbaafbb04,0xb9d1ba1e,0xb9e2ba4e,0xb928b97e,0xb8edb96c,0xb86eb8cd,0xb7afb866,0xb74bb80b,0xb54fb684,0xb5a2b679,0xb197b411,
0x362e3549,0x338330de,0x37e6370d,0x3651350e,0x38c0385c,0x38593788,0x397c3921,0x396a38e6,0x3a2439d3,0x3a5339e4,0x3ab63a70,0x3b0f3ab7,0x3b2e3af5,0x3b973b5a,0x3b8d3b61,0x3be83bc7,
0x3b703b9c,0x3bd03bef,0x3b033b3d,0x3b653ba2,0x3a793ac1,0x3ac03b19,0x39d53a2a,0x39e63a59,0x3919397a,0x38de3967,0x384938b4,0x3761384c,0x36cf37b4,0x34cc361d,0x34f035e2,0x302332e4,
0xb596b496,0xb244aecf,0xb783b690,0xb5e8b48a,0xb8a7b836,0xb83eb73a,0xb978b912,0xb965b8d7,0xba30b9d7,0xba5fb9e8,0xbacdba82,0xbb23bac8,0xbb4cbb10,0xbbacbb6f,0xbbaabb7f,0xbbf4bbd8,
0xbb8dbbb7,0xbbe0bbf9,0xbb1dbb5a,0xbb7abbb5,0xba8bbad9,0xbad0bb2d,0xb9d9ba36,0xb9eaba65,0xb90bb975,0xb8cfb963,0xb824b89a,0xb713b831,0xb651b750,0xb447b5b3,0xb43bb549,0xad58b1a4,
0x34fc33c0,0x31032bc0,0x371e3611,0x357e3405,0x388d3811,0x382436eb,0x39733903,0x396138c8,0x3a3c39db,0x3a6a39ec,0x3ae43a94,0x3b373ad9,0x3b673b2a,0x3bbe3b83,0x3bc33b9a,0x3bfc3be7,
0x3bed3bff,0x3bff3bea,0x3b8d3bc7,0x3bcc3bf5,0x3ae13b40,0x3b1d3b83,0x39ef3a70,0x39ff3a9b,0x38c0395e,0x3883394b,0x36c33816,0x357e3750,0x33833549,0x2e84332e,0x28cf3061,0xb0aca5b2,
0xaf7ea376,0x29663166,0xb514b2fd,0xb2bfad71,0xb809b69b,0xb734b555,0xb95cb8b9,0xb949b87b,0xba75b9f1,0xbaa1ba01,0xbb49bae9,0xbb8bbb25,0xbbcfbb96,0xbbf9bbd2,0xbc00bbf2,0xbbe3bbfe,
0xbbf6bc00,0xbbfcbbda,0xbb9fbbd6,0xbbd8bbfb,0xbaf0bb52,0xbb2cbb92,0xb9f3ba7b,0xba03baa6,0xb8b1b95a,0xb873b947,0xb673b7f6,0xb52cb718,0xb276b4de,0xac5eb251,0x2052ae39,0x321f2bf2,
0x2cf4a806,0xad3fb2d8,0x34a831ee,0x31e22a93,0x37db364b,0x36fc3502,0x395738a9,0x3944386b,0x3a8039f5,0x3aab3a05,0x3b5b3af8,0x3b993b33,0x3bdd3ba7,0x3bfd3bdd,0x3bff3bfa,0x3bd13bf9,
0x3bfd3bfd,0x3bf53bc6,0x3baf3be3,0x3be23bff,0x3b003b64,0x3b393ba0,0x39f73a86,0x3a083ab0,0x38a23955,0x38633942,0x362237bf,0x34d836e0,0x31663472,0x286b3172,0xaaf82b5c,0xb390ae84,
0xa8cf2cf4,0x2fc93423,0xb43bb0de,0xb103a484,0xb7a4b5fa,0xb6c3b4ae,0xb953b89a,0xb940b85c,0xba8bb9f9,0xbab6ba0a,0xbb6cbb07,0xbba6bb40,0xbbe8bbb7,0xbc00bbe7,0xbbfabbff,0xbbbabbf1,
0xbc00bbf6,0xbbebbbae,0xbbbebbed,0xbbebbc00,0xbb0fbb74,0xbb47bbad,0xb9fbba91,0xba0cbabb,0xb892b950,0xb854b93d,0xb5d1b788,0xb484b6a7,0xb055b405,0x9248b093,0x2e6ba484,0x347e3086,
0x98b6afe2,0xb128b4d8,0x339c2f97,0x3023a420,0x376c35a8,0x368a345a,0x394e388b,0x393b384c,0x3a9639fd,0x3ac03a0e,0x3b7c3b16,0x3bb33b4d,0x3bf23bc5,0x3c003bef,0x3bf03c00,0x3ba03be5,
0x3bde3b91,0x3b8a3af7,0x3bf23bff,0x3c003be3,0x3b533bb9,0x3b823bdf,0x3a103ac5,0x3a203aec,0x38443939,0x38033925,0x342f366d,0x31b03584,0xa8392f65,0xb15a1d7f,0xb531b1c9,0xb7e0b55b,
0x3269358a,0x35a83819,0xae842a61,0x205231e2,0xb651b405,0xb567b15a,0xb936b83c,0xb923b7f6,0xbacaba12,0xbaf0ba22,0xbbbebb5a,0xbbe3bb88,0xbbfdbbf5,0xbbddbc00,0xbb81bbd6,0xbadfbb7c,
0xbbcebb70,0xbb6dbac6,0xbbf8bbfb,0xbbffbbd6,0xbb60bbc4,0xbb8dbbe7,0xba14bacf,0xba24baf5,0xb834b934,0xb7e6b921,0xb3b4b634,0xb103b549,0x2c44ada3,0x326925b2,0x35e23309,0x384135f4,
0xb3a8b63a,0xb63fb869,0x2cc2ad58,0xa89db2f0,0x3617335f,0x352c30ac,0x3931382c,0x391e37d5,0x3ad43a16,0x3afa3a26,0x3bc93b66,0x3bea3b92,0x3bf93bfa,0x3bcf3bff,0x3b5f3bc5,0x3aad3b5d,
0x3bba3b4c,0x3b4d3a93,0x3bfc3bf6,0x3bfd3bc7,0x3b6c3bce,0x3b973bed,0x3a183ad9,0x3a283afe,0x3824392f,0x37c5391c,0x330935fa,0x3055350e,0xae6b2bc0,0xb377aa61,0xb690b423,0xb890b68a,
0x347236e5,0x36d438b6,0xa9fd2f7e,0x2c1233fd,0xb5dcb2b3,0xb4f0affb,0xb92db81c,0xb919b7b4,0xbaddba1a,0xbb03ba2a,0xbbd3bb72,0xbbf0bb9c,0xbbf2bbfe,0xbbbfbbfc,0xbb38bbaf,0xba77bb3c,
0xbba4bb23,0xbb2aba5b,0xbbffbbee,0xbbfabbb6,0xbb77bbd7,0xbba1bbf3,0xba1cbae2,0xba2cbb07,0xb813b92a,0xb7a4b917,0xb25db5bf,0xaf4cb4d2,0x3048a839,0x34412cf4,0x373a34c0,0x38dc371e,
0xb50eb78e,0xb767b901,0x24e9b0d1,0xadd5b484,0x35a23207,0x34b42e9d,0x3928380b,0x39143793,0x3ae73a1e,0x3b0c3a2e,0x3bdb3b7d,0x3bf53ba6,0x3be93c00,0x3bad3bf7,0x3b0d3b97,0x3a3e3b18,
0xb999b996,0xb889b85d,0xb99db99b,0xb8e0b8b5,0xb9a1b99f,0xb933b909,0xb9a6b9a4,0xb982b95b,0xb9aab9a8,0xb9cdb9a8,0xb9afb9ad,0xba15b9f2,0xb9b3b9b1,0xba58ba37,0xb9b8b9b5,0xba97ba78,
0xb9d6b9dc,0xbab0bad0,0xb9c9b9d0,0xba6bba8e,0xb9bcb9c3,0xba21ba47,0xb9afb9b5,0xb9d2b9fa,0xb9a1b9a8,0xb97db9a8,0xb994b99b,0xb924b951,0xb986b98d,0xb8c7b8f6,0xb979b980,0xb865b896,
0x3958394d,0x38403807,0x39703964,0x38ad3877,0x3986397b,0x391638e2,0x399d3992,0x39793948,0x39b339a8,0x39d639a8,0x39c939be,0x3a2d3a02,0x39df39d4,0x3a7e3a56,0x39f439e9,0x3ac73aa3,
0x3a113a1f,0x3ade3b02,0x39f43a02,0x3a903ab8,0x39d639e5,0x3a393a65,0x39b839c7,0x39da3a0b,0x399939a8,0x397439a8,0x39793989,0x3907393e,0x39583969,0x389438ce,0x39373948,0x381a3858,
0xb916b900,0xb7e8b75e,0xb941b92b,0xb87ab838,0xb96bb956,0xb8f8b8ba,0xb994b980,0xb970b935,0xb9bcb9a8,0xb9dfb9a8,0xb9e3b9d0,0xba45ba13,0xba09b9f6,0xbaa2ba74,0xba2dba1b,0xbaf4bacc,
0xba49ba5e,0xbb0abb30,0xba1dba33,0xbab3bae0,0xb9f0ba07,0xba50ba83,0xb9c0b9d8,0xb9e3ba1b,0xb990b9a8,0xb96bb9a8,0xb95db976,0xb8eab92b,0xb929b943,0xb85fb8a6,0xb8f3b90e,0xb79bb817,
0x38d138b0,0x374e36aa,0x391138f1,0x384537ee,0x394f3930,0x38db3891,0x398b396d,0x39663922,0x39c539a8,0x39e739a8,0x39fc39e1,0x3a5c3a23,0x3a313a17,0x3ac43a92,0x3a643a4b,0x3b1e3af3,
0x3a7e3a99,0x3b323b5a,0x3a453a62,0x3ad53b05,0x3a093a27,0x3a673aa0,0x39c939e9,0x39eb3a2b,0x398639a8,0x396239a8,0x39413964,0x38cc3918,0x38f8391d,0x382a387c,0x38ad38d3,0x36ff37ac,
0xb6afb5f1,0xb41ab1db,0xb80fb76a,0xb65fb540,0xb8bcb867,0xb840b775,0xb95db90e,0xb937b8bf,0xb9f0b9a8,0xba11b9a8,0xba73ba33,0xbac7ba71,0xbae5baae,0xbb57bb14,0xbb45bb17,0xbbbcbb8f,
0xbb57bb80,0xbbc6bbe6,0xbaf4bb28,0xbb63bb9b,0xba7ebabc,0xbad1bb20,0xb9f4ba3b,0xba15ba78,0xb958b9a8,0xb933b9a8,0xb8adb905,0xb830b8b5,0xb7e8b852,0xb625b748,0xb65fb726,0xb389b4f9,
0x360e3534,0x32de304e,0x37b236e3,0x35eb34b1,0x389e383d,0x3820371b,0x395438fb,0x392e38ab,0x39f839a8,0x3a1939a8,0x3a893a43,0x3adb3a7f,0x3b043ac9,0x3b6f3b2b,0x3b683b39,0x3bd03ba6,
0x3b783ba0,0x3bd93bf4,0x3b133b49,0x3b7a3bb1,0x3a933ad6,0x3ae53b36,0x39fc3a4b,0x3a1d3a87,0x394f39a8,0x392939a8,0x388e38f1,0x380f38a0,0x377a3828,0x35b136ee,0x35bc369e,0x32323469,
0xb56ab475,0xb185ad7e,0xb742b659,0xb576b420,0xb87fb812,0xb7feb6c1,0xb94ab8e7,0xb924b896,0xba00b9a8,0xba21b9a8,0xba9eba52,0xbaeeba8e,0xbb21bae3,0xbb85bb41,0xbb87bb58,0xbbe1bbbb,
0xbb96bbbc,0xbbe8bbfc,0xbb2fbb67,0xbb90bbc4,0xbaa9baf0,0xbaf7bb4b,0xba04ba5a,0xba25ba95,0xb946b9a8,0xb91fb9a8,0xb86fb8dd,0xb7ddb88c,0xb70ab7f9,0xb53ab693,0xb517b614,0xb0d7b3ae,
0x34c33365,0x302928b6,0x36d235ce,0x34ff331b,0x385f37cd,0x37bd3665,0x394138d3,0x391b3881,0x3a0939a8,0x3a2939a8,0x3ab33a62,0x3b013a9c,0x3b3d3afc,0x3b9a3b55,0x3ba33b74,0x3bef3bcd,
0x3bb03bd4,0x3bf43c00,0x3b4a3b82,0x3ba33bd5,0x3abd3b08,0x3b0a3b5f,0x3a0d3a69,0x3a2d3aa3,0x393c39a8,0x391639a8,0x385038c9,0x379b3877,0x369937a1,0x34c33637,0x346f3587,0x2ef53288,
0xad972248,0x2d6532a1,0xb487b1f4,0xb13ba91b,0xb77ab608,0xb66bb48d,0xb911b86d,0xb8eab817,0xba31b9a8,0xba50b9a8,0xbb13baaa,0xbb54bae0,0xbbacbb69,0xbbe4bbab,0xbbf8bbdc,0xbbf9bbfe,
0xbbfcbbff,0xbbf5bbc9,0xbbb5bbe3,0xbbe9bc00,0xbb1bbb72,0xbb5cbbb2,0xba35bab1,0xba54bae6,0xb90cb9a8,0xb8e5b9a8,0xb759b862,0xb648b80d,0xb44bb5da,0xb0beb45d,0xac38b160,0x2ec3a57f,
0x29b1abd9,0xb010b414,0x340e30cb,0x30421a48,0x373735ab,0x3625342c,0x39073858,0x38e03802,0x3a3939a8,0x3a5839a8,0x3b243ab8,0x3b633aed,0x3bbd3b7b,0x3bee3bb9,0x3bfe3be9,0x3bef3c00,
0x3bff3bf8,0x3be93baf,0x3bc53bee,0x3bf23c00,0x3b2c3b84,0x3b6a3bc0,0x3a3d3abf,0x3a5c3af3,0x390239a8,0x38db39a8,0x3715384d,0x360237ee,0x33a2357c,0x2f8b33f7,0x25e43036,0xb0bea3db,
0x96482f0e,0x316c34d5,0xb328af40,0xae912852,0xb6f4b54c,0xb5dfb396,0xb8fdb842,0xb8d6b7d8,0xba41b9a8,0xba60b9a8,0xbb35bac6,0xbb71baf9,0xbbccbb8c,0xbbf5bbc6,0xbc00bbf3,0xbbe2bbff,
0xbc00bbed,0xbbdabb91,0xbbd3bbf7,0xbbf8bbfd,0xbb3dbb95,0xbb78bbcb,0xba45bacc,0xba64baff,0xb8f8b9a8,0xb8d1b9a8,0xb6d2b838,0xb5bcb7c2,0xb2adb51d,0xad97b334,0x251bae14,0x32192aac,
0xa94db115,0xb2c6b593,0x32322ce7,0x2c9cac83,0x36af34ed,0x359932d2,0x38f3382d,0x38cc37ac,0x3a4939a8,0x3a6739a8,0x3b453ad3,0x3b7f3b05,0x3bd93b9d,0x3bfb3bd1,0x3bfe3bfa,0x3bd23bfb,
0x3bfc3bdd,0x3bc83b6e,0x3bdf3bfd,0x3bfd3bf8,0x3b4c3ba4,0x3b853bd6,0x3a4d3ad9,0x3a6b3b0b,0x38ee39a8,0x38c739a8,0x368d3822,0x35763796,0x31b634bd,0x2b43326f,0xac062b75,0xb371adb0,
0x340e364e,0x36a43887,0xa94d2edc,0x2d333408,0xb552b20d,0xb432ade2,0xb8c1b780,0xb899b6cc,0xba6fb9a8,0xba8cb9a8,0xbb8bbb11,0xbbb8bb3e,0xbbfebbdb,0xbbf9bbf7,0xbbbdbbf4,0xbb47bbbe,
0xbbb2bb46,0xbb35ba7c,0xbbffbbf0,0xbbf6bbb4,0xbb92bbe0,0xbbbdbbf9,0xba73bb17,0xba90bb43,0xb8bcb9a8,0xb894b9a8,0xb52fb76a,0xb40eb6b5,0xa6adb1aa,0x2e2dad1a,0x34633004,0x36f43451,
0xb4b7b705,0xb742b8d8,0x217fb099,0xaf27b499,0x350b3147,0x33d32c51,0x38b73753,0x388e369e,0x3a7639a8,0x3a9339a8,0x3b983b1d,0x3bc23b49,0x3c003be4,0x3bf33bfb,0x3ba53beb,0x3b213baa,
0x3b983b1a,0x3b0d3a3f,0x3c003be5,0x3bef3b9e,0x3b9e3be8,0x3bc63bfd,0x3a7a3b22,0x3a973b4e,0x38b239a8,0x388939a8,0x34e7373d,0x33893687,0x9cb630e4,0xb0102b11,0xb50bb12e,0xb790b4e1,
0x355e37b7,0x37dd3927,0x251b31c3,0x308d3529,0xb4c3b080,0xb340a97f,0xb8adb726,0xb884b670,0xba7eb9a8,0xba9bb9a8,0xbba3bb28,0xbbcbbb53,0xbc00bbec,0xbbebbbfe,0xbb89bbdf,0xbaf7bb93,
0xbb7abae9,0xbae1b9fe,0xbbffbbd7,0xbbe6bb86,0xbba9bbef,0xbbcfbbff,0xba81bb2e,0xba9ebb58,0xb8a8b9a8,0xb87fb9a8,0xb49fb710,0xb2f7b659,0x2884b01d,0x3109a7da,0x35b13257,0x38153570,
0xb602b832,0xb83ab972,0xaa7ab2ea,0xb185b5b6,0x347b2f72,0x32ad24b6,0x38a336f9,0x387a3642,0x3a8539a8,0x3aa239a8,0x3bae3b33,0x3bd33b5d,0x3bfd3bf2,0x3be13c00,0x3b6a3bd0,0x3acb3b79,
0x3b593ab5,0x3ab339ba,0x3bfc3bc7,0x3bdc3b6b,0x3bb33bf5,0x3bd73c00,0x3a893b39,0x3aa53b62,0x389e39a8,0x387439a8,0x345736e3,0x3263362b,0xac382eaa,0xb2011e48,0xb654b37d,0xb85fb5fd,
0xb99ab997,0xb89fb873,0xb99eb99c,0xb8f5b8ca,0xb9a3b9a0,0xb947b91e,0xb9a7b9a5,0xb995b96e,0xb9abb9a9,0xb9e0b9bb,0xb9b0b9ae,0xba26ba03,0xb9b4b9b2,0xba68ba48,0xb9b9b9b7,0xbaa6ba88,
0xb9d3b9d9,0xba9fbac0,0xb9c6b9cc,0xba59ba7d,0xb9b9b9bf,0xba0eba34,0xb9abb9b2,0xb9bdb9e6,0xb99eb9a5,0xb967b993,0xb991b997,0xb90db93b,0xb983b98a,0xb8aeb8de,0xb975b97c,0xb84cb87e,
0x395e3953,0x385c3824,0x3975396a,0x38c83892,0x398c3981,0x392f38fc,0x39a33997,0x39913961,0x39b939ae,0x39ec39bf,0x39cf39c4,0x3a423a18,0x39e439d9,0x3a913a6a,0x39f939ef,0x3ad93ab6,
0x3a0a3a18,0x3acb3af0,0x39ec39fb,0x3a7b3aa4,0x39cf39de,0x3a223a4f,0x39b039bf,0x39c139f3,0x399139a0,0x395a398e,0x39713981,0x38eb3923,0x39503961,0x387638b1,0x392f3940,0x37f63839,
0xb921b90b,0xb816b7a4,0xb94bb936,0xb89ab859,0xb975b961,0xb917b8d9,0xb99eb98a,0xb98cb953,0xb9c6b9b2,0xb9f9b9c4,0xb9ecb9d9,0xba5dba2c,0xba12b9ff,0xbab7ba8b,0xba36ba24,0xbb07bae1,
0xba3eba53,0xbaf5bb1d,0xba12ba28,0xba9bbaca,0xb9e4b9fb,0xba36ba6a,0xb9b4b9cc,0xb9c6b9ff,0xb983b99c,0xb94bb98a,0xb950b96a,0xb8c8b90b,0xb91cb936,0xb83cb883,0xb8e6b901,0xb750b7e6,
0x38e138c0,0x379e36fc,0x39213901,0x386b381e,0x395e3940,0x38fe38b6,0x399a397c,0x39883944,0x39d339b7,0x3a0539c8,0x3a0a39ef,0x3a773a40,0x3a3e3a24,0x3adc3aab,0x3a703a57,0x3b333b09,
0x3a703a8b,0x3b1c3b47,0x3a363a53,0x3abb3aed,0x39f93a18,0x3a4a3a84,0x39b939d9,0x39ca3a0c,0x39753997,0x393d3985,0x392f3953,0x38a438f2,0x38e6390b,0x38003854,0x389a38c0,0x36a73756,
0xb70db651,0xb4aeb309,0xb83cb7c5,0xb6ebb5d1,0xb8e6b892,0xb880b7fb,0xb983b936,0xb971b8fc,0xba12b9cc,0xba42b9de,0xba91ba53,0xbaefba9d,0xbafebaca,0xbb74bb37,0xbb5abb2e,0xbbcebba6,
0xbb40bb6c,0xbbb2bbd8,0xbad9bb0f,0xbb43bb80,0xba5dba9d,0xbaa6bafa,0xb9cfba18,0xb9e0ba48,0xb92fb981,0xb8f5b96e,0xb880b8d9,0xb7d5b873,0xb788b824,0xb590b6b8,0xb5fab6c3,0xb251b460,
0x367935a2,0x34113197,0x380b374b,0x3684354f,0x38cd386e,0x386637af,0x397e3928,0x396c38ed,0x3a1e39d1,0x3a4e39e2,0x3aa93a66,0x3b043aaf,0x3b1f3ae7,0x3b8c3b4e,0x3b7d3b51,0x3be03bbd,
0x3b613b8d,0x3bc73be8,0x3af53b2e,0x3b5a3b97,0x3a703ab6,0x3ab73b0f,0x39d33a24,0x39e43a53,0x3921397c,0x38e6396a,0x385c38c0,0x37883859,0x370d37e6,0x350e3651,0x3549362e,0x30de3383,
0xb5e2b4f0,0xb2e4b023,0xb7b4b6cf,0xb61db4cc,0xb8b4b849,0xb84cb761,0xb97ab919,0xb967b8de,0xba2ab9d5,0xba59b9e6,0xbac1ba79,0xbb19bac0,0xbb3dbb03,0xbba2bb65,0xbb9cbb70,0xbbefbbd0,
0xbb7fbbaa,0xbbd8bbf4,0xbb10bb4c,0xbb6fbbac,0xba82bacd,0xbac8bb23,0xb9d7ba30,0xb9e8ba5f,0xb912b978,0xb8d7b965,0xb836b8a7,0xb73ab83e,0xb690b783,0xb48ab5e8,0xb496b596,0xaecfb244,
0x3549343b,0x31a42d58,0x37503651,0x35b33447,0x389a3824,0x38313713,0x3975390b,0x396338cf,0x3a3639d9,0x3a6539ea,0x3ad93a8b,0x3b2d3ad0,0x3b5a3b1d,0x3bb53b7a,0x3bb73b8d,0x3bf93be0,
0x3b9a3bc3,0x3be73bfc,0x3b2a3b67,0x3b833bbe,0x3a943ae4,0x3ad93b37,0x39db3a3c,0x39ec3a6a,0x39033973,0x38c83961,0x3811388d,0x36eb3824,0x3611371e,0x3405357e,0x33c034fc,0x2bc03103,
0xb061a8cf,0x25b230ac,0xb549b383,0xb32eae84,0xb816b6c3,0xb750b57e,0xb95eb8c0,0xb94bb883,0xba70b9ef,0xba9bb9ff,0xbb40bae1,0xbb83bb1d,0xbbc7bb8d,0xbbf5bbcc,0xbbffbbed,0xbbeabbff,
0xbbf2bc00,0xbbfebbe3,0xbb96bbcf,0xbbd2bbf9,0xbae9bb49,0xbb25bb8b,0xb9f1ba75,0xba01baa1,0xb8b9b95c,0xb87bb949,0xb69bb809,0xb555b734,0xb2fdb514,0xad71b2bf,0xa376af7e,0x31662966,
0x2e39a052,0xabf2b21f,0x34de3276,0x32512c5e,0x37f63673,0x3718352c,0x395a38b1,0x39473873,0x3a7b39f3,0x3aa63a03,0x3b523af0,0x3b923b2c,0x3bd63b9f,0x3bfb3bd8,0x3c003bf6,0x3bda3bfc,
0x3bfa3bff,0x3bf93bd1,0x3ba73bdd,0x3bdd3bfd,0x3af83b5b,0x3b333b99,0x39f53a80,0x3a053aab,0x38a93957,0x386b3944,0x364b37db,0x350236fc,0x31ee34a8,0x2a9331e2,0xa8062cf4,0xb2d8ad3f,
0xab5c2af8,0x2e843390,0xb472b166,0xb172a86b,0xb7bfb622,0xb6e0b4d8,0xb955b8a2,0xb942b863,0xba86b9f7,0xbab0ba08,0xbb64bb00,0xbba0bb39,0xbbe3bbaf,0xbbffbbe2,0xbbfdbbfd,0xbbc6bbf5,
0xbbffbbfa,0xbbf1bbba,0xbbb7bbe8,0xbbe7bc00,0xbb07bb6c,0xbb40bba6,0xb9f9ba8b,0xba0abab6,0xb89ab953,0xb85cb940,0xb5fab7a4,0xb4aeb6c3,0xb0deb43b,0xa484b103,0x2cf4a8cf,0x34232fc9,
0x2484ae6b,0xb086b47e,0x34053055,0x30931248,0x378835d1,0x36a73484,0x39503892,0x393d3854,0x3a9139fb,0x3abb3a0c,0x3b743b0f,0x3bad3b47,0x3bed3bbe,0x3c003beb,0x3bf63c00,0x3bae3beb,
0x3c003bf0,0x3be53ba0,0x3bc53bf2,0x3bef3c00,0x3b163b7c,0x3b4d3bb3,0x39fd3a96,0x3a0e3ac0,0x388b394e,0x384c393b,0x35a8376c,0x345a368a,0x2f97339c,0xa4203023,0xafe298b6,0xb4d8b128,
0x31c93531,0x355b37e0,0xaf652839,0x9d7f315a,0xb66db42f,0xb584b1b0,0xb939b844,0xb925b803,0xbac5ba10,0xbaecba20,0xbbb9bb53,0xbbdfbb82,0xbbffbbf2,0xbbe3bc00,0xbb91bbde,0xbaf7bb8a,
0xbbd6bb81,0xbb7cbadf,0xbbf5bbfd,0xbc00bbdd,0xbb5abbbe,0xbb88bbe3,0xba12baca,0xba22baf0,0xb83cb936,0xb7f6b923,0xb405b651,0xb15ab567,0x2a61ae84,0x31e22052,0x358a3269,0x381935a8,
0xb309b5e2,0xb5f4b841,0x2da3ac44,0xa5b2b269,0x363433b4,0x35493103,0x39343834,0x392137e6,0x3acf3a14,0x3af53a24,0x3bc43b60,0x3be73b8d,0x3bfb3bf8,0x3bd63bff,0x3b703bce,0x3ac63b6d,
0x3bc53b5f,0x3b5d3aad,0x3bfa3bf9,0x3bff3bcf,0x3b663bc9,0x3b923bea,0x3a163ad4,0x3a263afa,0x382c3931,0x37d5391e,0x335f3617,0x30ac352c,0xad582cc2,0xb2f0a89d,0xb63ab3a8,0xb869b63f,
0x34233690,0x368a3890,0xabc02e6b,0x2a613377,0xb5fab309,0xb50eb055,0xb92fb824,0xb91cb7c5,0xbad9ba18,0xbafeba28,0xbbcebb6c,0xbbedbb97,0xbbf6bbfc,0xbbc7bbfd,0xbb4cbbba,0xba93bb4d,
0xbbafbb38,0xbb3cba77,0xbbfebbf2,0xbbfcbbbf,0xbb72bbd3,0xbb9cbbf0,0xba1abadd,0xba2abb03,0xb81cb92d,0xb7b4b919,0xb2b3b5dc,0xaffbb4f0,0x2f7ea9fd,0x33fd2c12,0x36e53472,0x38b636d4,
0xb4c0b73a,0xb71eb8dc,0x2839b048,0xacf4b441,0x35bf325d,0x34d22f4c,0x392a3813,0x391737a4,0x3ae23a1c,0x3b073a2c,0x3bd73b77,0x3bf33ba1,0x3bee3bff,0x3bb63bfa,0x3b233ba4,0x3a5b3b2a,
0x3b973b0d,0x3b183a3e,0x3c003be9,0x3bf73bad,0x3b7d3bdb,0x3ba63bf5,0x3a1e3ae7,0x3a2e3b0c,0x380b3928,0x37933914,0x320735a2,0x2e9d34b4,0xb0d124e9,0xb484add5,0xb78eb50e,0xb901b767,
0xb97239ba,0x39dc3996,0xb8323ab5,0x3ad0385d,0x3927b9fe,0xba1fb94d,0x37b7bae9,0xbb02b807,0xb8d83a3f,0x3a5e3900,0xb7053b1a,0x3b30375e,0x3887ba7c,0xba99b8b0,0x364ebb46,0xbb5ab6aa,
0xb90039dc,0x3a3f3972,0xad7e3be6,0x3bf83115,0x3807ba99,0xbae9b887,0xabd9bc00,0xbbfca248,0xb5f13b30,0x3b6e3705,0x32a13bed,0x3bd4b04e,0x3365bba0,0xbbc9b4d5,0xb593bbaf,0xbb803475,
0xb88739fe,0x3a99394d,0x35f13bbc,0x3b6eb414,0x3593bb1a,0xbb80b75e,0xb8b0bb02,0xba7c37b7,0xaf0e3bc9,0x3bf43365,0x3a1f39dc,0x3927b972,0xb04ebc00,0xbbed2248,0xbb30b85d,0xb7053ab5,
0xb8073a1f,0x3ae93927,0x39fe3a3f,0x394db900,0x31dbbb80,0xbbddb593,0xbb6eb832,0xb5f13ad0,0x31153c00,0x3be62248,0x3bff32a1,0x28b6bbd4,0xb7b7bb91,0xbb023534,0xbba0304e,0x34d53bed,
0xb7053a3f,0x3b303900,0x3bbc375e,0x3414bb1a,0x2248bbc9,0xbc00b365,0xbbdda8b6,0x31db3bff,0x36aa3bd4,0x3b46b2a1,0x3a7cb64e,0xb8b0bb5a,0xba1fba5e,0xb92738d8,0xb7b739fe,0x3b02394d,
0xb5f13a5e,0x3b6e38d8,0x3bd42bd9,0xb2a1bbfc,0xb115bbf4,0xbbe6af0e,0xb9dc375e,0x39723b1a,0x39273b46,0x3a1fb6aa,0x3475bad0,0xbbafb832,0xbb91b887,0xb5343a99,0x34143c00,0x3bbc2248,
0xb4d53a7c,0x3ba038b0,0x3a3fb593,0xb900bb80,0xb534bc00,0xbb912248,0xb4143ab5,0x3bbc385d,0x3a993a5e,0x3887b8d8,0xb5f1bbfc,0xbb6e2bd9,0xbbffb475,0x28b63baf,0x3ad03a1f,0x3832b927,
0xb3653a99,0x3bc93887,0x36aab996,0xbb46b9ba,0xb7b7bbed,0xbb02304e,0x34d53bfc,0x3ba02bd9,0x3b913927,0x3534ba1f,0xbae9ba3f,0xb8073900,0xbb5a28b6,0x364e3bff,0x3bd43115,0xb2a1bbe6,
0xb1153ab5,0x3be6385d,0xa8b6bb6e,0xbbffb5f1,0xb900bbbc,0xba3f3414,0x3a1f3b30,0x3927b705,0x3bfc375e,0x2bd9bb1a,0xbbedb475,0x304e3baf,0xb9ba3593,0x39963b80,0x3887b832,0xba99bad0,
0xad7e3ad0,0x3bf83832,0xb7b7bbff,0xbb0228b6,0xb9febb6e,0xb94d35f1,0x3bed3887,0x304eba99,0x3bd43414,0xb2a1bbbc,0xb9963534,0x39ba3b91,0xb6aa3900,0x3b463a3f,0xb115bba0,0xbbe6b4d5,
0xa2483ae9,0x3c003807,0xba99bb30,0xb8873705,0xbad0bb02,0xb83237b7,0x3b462d7e,0xb6aabbf8,0x3b1a28b6,0xb75ebbff,0xaf0e3a7c,0x3bf438b0,0xabd93ab5,0x3bfc385d,0xba5ebb5a,0xb8d8364e,
0x2bd93b02,0x3bfc37b7,0xbbedb927,0xb04e3a1f,0xbb6eba7c,0xb5f138b0,0x385db6aa,0xbab5bb46,0x39dcb1db,0xb972bbdd,0x38323c00,0x3ad02248,0x34d53bbc,0x3ba03414,0xbbf4b705,0x2f0e3b30,
0x304e3b1a,0x3bed375e,0xbb91b475,0x35343baf,0xbbd4b9dc,0xb2a13972,0x2248ba7c,0xbc00b8b0,0x3832b64e,0xbad0bb5a,0x3b803a99,0x3593b887,0x39003bfc,0x3a3fabd9,0xb9273414,0x3a1f3bbc,
0x32a13b30,0x3bd43705,0xb996304e,0x39ba3bed,0xbbffb927,0xa8b63a1f,0xb832bbf4,0xbad0af0e,0x3475b8b0,0xbbafba7c,0x3ba03593,0xb4d5bb80,0x3ae93b6e,0x3807b5f1,0x2bd93a99,0x3bfc3887,
0x34753b46,0x3baf36aa,0xb4d53832,0x3ba03ad0,0xbbedb85d,0x304e3ab5,0xbb30bb5a,0xb705364e,0x2248b9fe,0xbc00b94d,0x3887b414,0xba99bbbc,0x3be63a1f,0x3115b927,0x39dc3bf4,0x3972af0e,
0x35933b5a,0x3b80364e,0x31153a99,0x3be63887,0xbba0b705,0x34d53b30,0xbbf4b8d8,0x2f0e3a5e,0xb414bb02,0xbbbcb7b7,0xabd9ba1f,0xbbfcb927,0x3bd43832,0xb2a1bad0,0x3c003972,0xa248b9dc,
0x36aa3b6e,0x3b4635f1,0x38b03bdd,0x3a7c31db,0xbb1ab534,0x375e3b91,0xba3fb04e,0x39003bed,0xb807bbaf,0xbae9b475,0xb94dbbf8,0xb9fead7e,0x3ab53365,0xb85dbbc9,0x39ba28b6,0xb996bbff,
0x37b73b80,0x3b023593,0x3b1a3bc9,0x375eb365,0xba5eb2a1,0x38d83bd4,0xb53435f1,0x3b913b6e,0xb9babbfc,0xb996abd9,0xbbddbae9,0xb1db3807,0x38b0ad7e,0xba7cbbf8,0x28b6b900,0xbbffba3f,
0x385d3b91,0x3ab53534,0x3c003a5e,0x2248b8d8,0xb972ad7e,0x39dc3bf8,0x33653a3f,0x3bc93900,0xbb02bbe6,0xb7b73115,0xbb1ab6aa,0x375e3b46,0x3414b64e,0xbbbcbb5a,0xb94dbbdd,0xb9feb1db,
0x38d83ba0,0x3a5e34d5,0x3b3037b7,0xb705bb02,0xb85d28b6,0x3ab53bff,0x39ba3be6,0x39963115,0xbbc9bb6e,0xb36535f1,0xb6aa31db,0x3b463bdd,0xaf0eb94d,0xbbf4b9fe,0xbbf8bae9,0xad7e3807,
0x394d3baf,0x39fe3475,0x38d82d7e,0xba5ebbf8,0xb64e3115,0x3b5a3be6,0x3bd43b80,0x32a1b593,0xbbffba99,0x28b63887,0x336539ba,0x3bc93996,0xb75ebae9,0xbb1ab807,0xba3fb534,0x39003b91,
0x39ba3bbc,0x39963414,0x31dbb534,0xbbddbb91,0xb3653475,0x3bc93baf,0x3b803927,0xb593ba1f,0xbba0b972,0x34d539dc,0x3a3f3be6,0x39003115,0xb9febbd4,0xb94db2a1,0xb04e35f1,0x3bed3b6e,
0x3a1f3bc9,0x39273365,0xb475b972,0xbbafb9dc,0xabd9364e,0x3bfc3b5a,0x38d831db,0xba5ebbdd,0xbab5b807,0x385d3ae9,0x3c003b30,0x2248b705,0xbb80bbf4,0xb5932f0e,0x38b03b1a,0x3a7c375e,
0x3a7c3bd4,0x38b032a1,0xb972bb5a,0xb9dcb64e,0x2f0e3807,0x3bf43ae9,0x2d7eb534,0xbbf8bb91,0xb94db4d5,0x39fe3ba0,0x3a5e37b7,0xb8d8bb02,0xbc00bb46,0x224836aa,0x3bdd3bc9,0x31dbb365,
0x3ad03bdd,0x383231db,0xbb80bc00,0xb5932248,0x347538d8,0x3baf3a5e,0xb75eb9fe,0xbb1ab94d,0xb705ad7e,0x3b303bf8,0x3414af0e,0xbbbcbbf4,0xbb6eb9dc,0x35f13972,0x3ab538b0,0xb85dba7c,
0x3b1a3be6,0x375e3115,0xbbf4bb46,0x2f0e36aa,0x37053996,0x3b3039ba,0xbae9bbd4,0xb807b2a1,0xb1db304e,0x3bdd3bed,0xb64eb94d,0xbb5ab9fe,0xb9dcb7b7,0x39723b02,0x3365ad7e,0xbbc9bbf8,
0x3b5a3bed,0x364e304e,0xbab5b94d,0x385d39fe,0x38b03a3f,0x3a7c3900,0xbbffbba0,0x28b634d5,0x2d7e3593,0x3bf83b80,0xbb02bbc9,0xb7b7b365,0xb705b1db,0x3b303bdd,0xb807b9ba,0xbae9b996,
0x3b913bf4,0x35342f0e,0xb807b4d5,0x3ae93ba0,0x39ba3ad0,0x39963832,0xba99b972,0x388739dc,0x3593385d,0x3b803ab5,0xbbe6bb6e,0x311535f1,0xad7e304e,0x3bf83bed,0xbbafbbfc,0xb475abd9,
0x3bbc3bf8,0x34142d7e,0xabd92f0e,0x3bfc3bf4,0x3a993b46,0x388736aa,0xb64eb365,0x3b5a3bc9,0x38b039ba,0x3a7c3996,0xb972b85d,0x39dc3ab5,0x34753705,0x3baf3b30,0xbb1aba5e,0x375e38d8,
0x3bdd3bfc,0x31db2bd9,0x364e3807,0x3b5a3ae9,0x3b463ba0,0x36aa34d5,0x31153475,0x3be63baf,0x3a3f3ad0,0x39003832,0xad7e28b6,0x3bf83bff,0x38d83996,0x3a5e39ba,0xb534b2a1,0x3b913bd4,
0x3bf43bff,0x2f0e28b6,0x3a1f3a7c,0x392738b0,0x3bbc3bdd,0x341431db,0x394d39ba,0x39fe3996,0x3b5a3b91,0x364e3534,0x385d38d8,0x3ab53a5e,0x3ad03b1a,0x3832375e,0x36aa37b7,0x3b463b02,
0x3bff3c00,0x28b62248,0x3bc93bd4,0x336532a1,0x3bf83bfc,0x2d7e2bd9,0x3baf3bbc,0x34753414,0x3bed3bf4,0x304e2f0e,0x3b913ba0,0x353434d5,0x3bdd3be6,0x31db3115,0x3b6e3b80,0x35f13593,
0xb5933b6e,0x3b8035f1,0xb1153bdd,0x3be631db,0x34d5bb91,0xbba0b534,0x2f0ebbed,0xbbf4b04e,0xb4143baf,0x3bbc3475,0xabd93bf8,0x3bfc2d7e,0x32a1bbc9,0xbbd4b365,0x2248bbff,0xbc00a8b6,
0x37b73b46,0x3b02b6aa,0x3b1a3832,0x375ebad0,0xb8d8bab5,0xba5e385d,0xbb91b64e,0xb5343b5a,0x39ba39fe,0x3996b94d,0x3bdd3414,0x31dbbbbc,0xba7cb927,0xb8b03a1f,0xbbffaf0e,0xa8b63bf4,
0x3bd43534,0x32a1bb91,0x39bab8d8,0xb996ba5e,0xbbffad7e,0x28b63bf8,0xb8323a3f,0x3ad03900,0x3bafb115,0xb475bbe6,0x34d5bb46,0xbba0b6aa,0xbae9364e,0x38073b5a,0xabd93bdd,0x3bfc31db,
0x3a5eb75e,0xb8d8bb1a,0xb705bbaf,0xbb303475,0xb85d39dc,0x3ab53972,0x39ba3a7c,0x3996b8b0,0x3365bb5a,0xbbc9b64e,0xbb46b887,0xb6aa3a99,0x2f0e3bfc,0x3bf42bd9,0x3bf83414,0x2d7ebbbc,
0x2bd9bbaf,0xbbfcb475,0xbbedad7e,0x304e3bf8,0x35f13be6,0x3b6eb115,0x3ab5b593,0xb85dbb80,0xb9dcba99,0xb9723887,0xb83239ba,0x3ad03996,0x3ba03807,0x34d5bae9,0x2f0ebb91,0xbbf4b534,
0xb9babae9,0xb9963807,0xb1db3b30,0x3bdd3705,0x3bc937b7,0x3365bb02,0xb593bbf8,0xbb802d7e,0xbba028b6,0x34d53bff,0x3a3f3a7c,0x3900b8b0,0x394db85d,0xb9febab5,0xbbedb64e,0xb04e3b5a,
0xbbf8b365,0x2d7e3bc9,0x3b0239dc,0x37b7b972,0x39feb64e,0xb94dbb5a,0xbbedb1db,0x304e3bdd,0xb2a13ae9,0x3bd43807,0x39bab705,0xb996bb30,0xb6aabbf4,0xbb462f0e,0xb1153b1a,0x3be6375e,
0xb8b0385d,0x3a7c3ab5,0x39dcb5f1,0xb972bb6e,0xaf0ebbbc,0xbbf4b414,0xad7e3b30,0x3bf83705,0x39fe3b1a,0x394db75e,0xb8d8bbaf,0xba5e3475,0xbc00b593,0x22483b80,0x3bdd3832,0x31dbbad0,
0x33653bdd,0x3bc931db,0xb6aabc00,0xbb462248,0xbb02ba5e,0xb7b738d8,0x3ba0394d,0x34d5b9fe,0x3b912d7e,0xb534bbf8,0xbae92f0e,0x38073bf4,0xb64e3972,0x3b5a39dc,0x32a1ba7c,0xbbd4b8b0,
0x3b1a3a7c,0x375eb8b0,0xbbf4b593,0x2f0e3b80,0xbb30a248,0x37053c00,0x3807b85d,0xbae9bab5,0x31dbba5e,0xbbddb8d8,0x364e3bfc,0x3b5a2bd9,0x39723baf,0x39dcb475,0xbbc9b927,0xb3653a1f,
0x3b6e304e,0xb5f1bbed,0xb2a139fe,0x3bd4394d,0xb1153a3f,0x3be63900,0xb9dcbba0,0xb97234d5,0xba1fbb80,0xb9273593,0x3baf3365,0xb475bbc9,0x3b9131db,0xb534bbdd,0xb41439ba,0x3bbc3996,
0x3534b900,0xbb91ba3f,0x3ae93b1a,0x3807b75e,0x39ba3bc9,0x3996b365,0xba9928b6,0x38873bff,0xbb80b2a1,0x35933bd4,0xb115bb5a,0xbbe6b64e,0x2d7eba5e,0xbbf8b8d8,0x3baf39fe,0x3475b94d,
0xb807bbf8,0xbae9ad7e,0x39feaf0e,0xb94dbbf4,0x3bdd36aa,0xb1dbbb46,0x35f13bc9,0x3b6e3365,0xb11539ba,0x3be63996,0xbbffb85d,0x28b63ab5,0xbb02bb30,0xb7b73705,0x34d5b8d8,0xbba0ba5e,
0xbbddb9fe,0xb1db394d,0xb64ebbbc,0xbb5ab414,0x36aab75e,0xbb46bb1a,0x3be637b7,0xb115bb02,0x3a3f3bc9,0x3900b365,0xad7e39dc,0x3bf83972,0xba5ea248,0x38d83c00,0xbb91bab5,0xb534385d,
0xba3fa8b6,0x39003bff,0xbbf8b8b0,0x2d7e3a7c,0xb807bbdd,0xbae9b1db,0x2bd9b9ba,0xbbfcb996,0x3b6e3534,0xb5f1bb91,0x3bd43a5e,0x32a1b8d8,0x33653b1a,0x3bc9375e,0xb59337b7,0x3b803b02,
0xa8b63996,0x3bff39ba,0xb365385d,0x3bc93ab5,0xbbf8b9fe,0xad7e394d,0xbbafbae9,0xb4753807,0x304eb900,0xbbedba3f,0x3534b75e,0xbb91bb1a,0x3bdd3a7c,0x31dbb8b0,0x3b6e3b46,0x35f1b6aa,
0x39dc3c00,0x3972a248,0x3ad03bd4,0x3832b2a1,0xb9272bd9,0x3a1f3bfc,0xb7b73414,0x3b023bbc,0xba5ebbf4,0xb8d82f0e,0xbb30bba0,0xb70534d5,0x3887b115,0xba99bbe6,0x364eb593,0xbb5abb80,
0x3bf43972,0xaf0eb9dc,0x3a1f3115,0xb927bbe6,0x34143a99,0x3bbc3887,0x39fe3c00,0x394d2248,0xbb5ab705,0x364e3b30,0xb85d304e,0x3ab53bed,0xb832bba0,0xbad0b4d5,0xbb46bbaf,0xb6aa3475,
0x3887abd9,0xba99bbfc,0xb5f1bae9,0xbb6eb807,0x3b803ba0,0x3593b4d5,0x3a7c3475,0xb8b0bbaf,0xaf0e3832,0x3bf43ad0,0x3a1f3bff,0x392728b6,0xbbedb996,0x304e39ba,0xb70532a1,0x3b303bd4,
0xb414ba1f,0xbbbcb927,0xbbfcba3f,0x2bd93900,0x3a993593,0xb887bb80,0xb64ebad0,0xbb5ab832,0x3a7c3c00,0x38b02248,0x39dc32a1,0xb972bbd4,0xb4753534,0x3baf3b91,0x3b1a3bed,0x375eb04e,
0xbb30bbf4,0xb7052f0e,0xb41434d5,0x3bbc3ba0,0x2248b832,0xbc00bad0,0xbbddb9dc,0x31db3972,0x3b46385d,0xb6aabab5,0xb8b0bb6e,0xba7cb5f1,0x3a1f3bed,0x3927304e,0x37b7abd9,0xbb02bbfc,
0xbb5ab8d8,0x364e3a5e,0x3ab53bfc,0x385d2bd9,0xba7cbbf4,0xb8b0af0e,0xa8b6375e,0x3bff3b1a,0x2d7eb6aa,0xbbf8bb46,0xbb02b832,0x37b73ad0,0x3b303887,0xb705ba99,0xbae9bc00,0xb807a248,
0xb4d53115,0x3ba03be6,0x3a3f36aa,0xb900bb46,0xbb91b996,0x353439ba,0x3bbc3bd4,0x3414b2a1,0xba99bbed,0xb887b04e,0x35f139fe,0x3b6e394d,0xa8b6b7b7,0xbbffbb02,0xb832ad7e,0x3ad03bf8,
0x38323a99,0x3ad03887,0xb593b996,0xbb80b9ba,0xb475304e,0x3baf3bed,0x375e2bd9,0xbb1abbfc,0xbb30b927,0x37053a1f,0x3bbc3a3f,0xb414b900,0xbb6ebbff,0xb5f128b6,0x3ab53be6,0x385d3115,
0x3be63bd4,0x3115b2a1,0xbbffbb5a,0x28b6364e,0x39003ae9,0x3a3f3807,0xba1fbb91,0xb927b534,0xabd934d5,0x3bfc3ba0,0xb04eb7b7,0xbbedbb02,0xb9bab6aa,0x39963b46,0x38873365,0xba99bbc9,
0x3a1f3832,0xb927bad0,0xb47528b6,0x3baf3bff,0x3bfc3b6e,0xabd9b5f1,0xba5eb887,0x38d83a99,0x3ab53bbc,0x385d3414,0xbc00bb91,0x22483534,0x35933900,0x3b803a3f,0xba7cbba0,0xb8b0b4d5,
0x2248b414,0xbc00bbbc,0x3a993b91,0x38873534,0x38323475,0xbad0bbaf,0x36aa3927,0x3b463a1f,0x3b1a39dc,0xb75eb972,0xaf0e3115,0x3bf43be6,0x3bfc3bd4,0x2bd9b2a1,0xb8d8b5f1,0x3a5e3b6e,
0xb9febb02,0xb94db7b7,0x3a5e3927,0xb8d8ba1f,0xb64eb8b0,0xbb5aba7c,0x3bd43b46,0xb2a1b6aa,0x28b6b1db,0xbbffbbdd,0x3bc93c00,0x33652248,0x375e3414,0xbb1abbbc,0x3a3f3b30,0x39003705,
0xbbedbba0,0x304e34d5,0xb534b7b7,0xbb91bb02,0xbbd4bbff,0xb2a1a8b6,0x2248b115,0xbc00bbe6,0xbad0bb6e,0xb832b5f1,0x359331db,0xbb80bbdd,0xb900b9fe,0xba3fb94d,0x39273807,0xba1fbae9,
0xb85db705,0x3ab53b30,0xbc00bbed,0x2248304e,0xb9dcb927,0x39723a1f,0xbbc9bbf4,0xb365af0e,0xbb02ba7c,0x37b738b0,0xbb1abb80,0xb75eb593,0xbbbcbb6e,0x341435f1,0xb9feba99,0xb94db887,
0x34753593,0x3baf3b80,0xb4d5b365,0x3ba03bc9,0x304e32a1,0x3bed3bd4,0xb705b5f1,0x3b303b6e,0xa2482bd9,0x3c003bfc,0xb887b807,0x3a993ae9,0xb115ad7e,0x3be63bf8,0xb972b900,0x39dc3a3f,
0x3b463b5a,0x36aa364e,0x3a7c3a99,0x38b03887,0x3b1a3b30,0x375e3705,0x3a3f3a5e,0x390038d8,0x3ae93b02,0x380737b7,0x39fe3a1f,0x394d3927,0x3ab53ad0,0x385d3832,0x39ba39dc,0x39963972,
0x28b63c00,0x3bffa248,0x33653bd4,0x3bc9b2a1,0xad7ebbfc,0xbbf82bd9,0xb475bbbc,0xbbaf3414,0x304e3bf4,0x3bedaf0e,0x35343ba0,0x3b91b4d5,0xb1dbbbe6,0xbbdd3115,0xb5f1bb80,0xbb6e3593,
0x3bf4a8b6,0xaf0ebbff,0x3a1fb8b0,0xb927ba7c,0xbbbc31db,0x34143bdd,0xb94d3996,0x39fe39ba,0x3b5ab534,0xb64ebb91,0x385dba5e,0xbab5b8d8,0xbad0375e,0x38323b1a,0xb6aa3b02,0x3b4637b7,
0xb1dbbbfc,0xbbdd2bd9,0xbb5ab807,0xb64e3ae9,0x36aa3ba0,0x3b46b4d5,0x3be63475,0x3115bbaf,0xb900bad0,0xba3f3832,0xbbf8a8b6,0x2d7e3bff,0x3a5e3996,0x38d8b9ba,0x3b91b2a1,0xb534bbd4,
0xbbbc2d7e,0x34143bf8,0x2bd93bf4,0x3bfc2f0e,0x3a99b6aa,0xb887bb46,0xb64ebbc9,0xbb5a3365,0xb8b03996,0x3a7c39ba,0x39723ab5,0x39dcb85d,0x3475bb30,0xbbafb705,0xbb1ab8d8,0xb75e3a5e,
0x35343bf4,0x3b91af0e,0x3ae9b4d5,0xb807bba0,0xb996bad0,0xb9ba3832,0xb8873972,0x3a9939dc,0x3b80385d,0x3593bab5,0x3115bb6e,0xbbe6b5f1,0xbbf8b04e,0x2d7e3bed,0x34753bfc,0x3bafabd9,
0x3b5ab04e,0xb64ebbed,0xbab5b9fe,0xb85d394d,0xb8b03900,0x3a7c3a3f,0x3bff34d5,0x28b6bba0,0x2d7ebb80,0xbbf8b593,0xbb023365,0x37b73bc9,0x37053bdd,0x3b30b1db,0x3807b996,0xbae9b9ba,
0xb75ebbe6,0xbb1a3115,0xaf0e3b46,0x3bf436aa,0x3b303996,0x3705b9ba,0xb807bbd4,0xbae932a1,0xbbddb04e,0x31db3bed,0x3b5a394d,0x364eb9fe,0x3972b7b7,0xb9dcbb02,0xbbc9ad7e,0x33653bf8,
0xbad031db,0x38323bdd,0x3b802248,0xb593bc00,0x3475ba5e,0xbbafb8d8,0xb75e394d,0x3b1a39fe,0x37053bf8,0x3b30ad7e,0xb414bbf4,0xbbbcaf0e,0xbb6eb972,0xb5f139dc,0x3ab53a7c,0x385db8b0,
0x38b03bd4,0x3a7cb2a1,0xb9dcbb5a,0xb972364e,0xbbf4b807,0xaf0e3ae9,0x3bf83534,0xad7ebb91,0x39feb4d5,0xb94dbba0,0xb8d837b7,0x3a5e3b02,0xa2483b46,0x3c0036aa,0xb1dbbbc9,0xbbddb365,
0x3a1fb365,0xb927bbc9,0xb47539dc,0x3baf3972,0x2bd93b5a,0x3bfc364e,0xb8d8bbdd,0xba5e31db,0xbab5bae9,0xb85d3807,0x3c003705,0xa248bb30,0x3b802f0e,0xb593bbf4,0xb8b0375e,0x3a7c3b1a,
0xb996bbbc,0xb9ba3414,0x3bdd3534,0xb1dbbb91,0x3bc93475,0xb365bbaf,0xb5933927,0x3b803a1f,0xb4d53972,0x3ba039dc,0xb900bbe6,0xba3f3115,0xb94dbbd4,0xb9fe32a1,0x3bed35f1,0xb04ebb6e,
0xb94d3475,0x39fe3baf,0xb8d8bbf8,0xba5e2d7e,0xb64ebbe6,0xbb5ab115,0x3bd43593,0xb2a1bb80,0x3bff3887,0x28b6ba99,0xb3653996,0x3bc939ba,0xb75e3807,0x3b1a3ae9,0xba3fbb91,0xb9003534,
0x3a5e3ba0,0x38d8b4d5,0xb70537b7,0x3b303b02,0xbab5a8b6,0x385d3bff,0xb996bbe6,0xb9ba3115,0xb365bb6e,0xbbc9b5f1,0x3b4631db,0xb6aabbdd,0x3bf4394d,0x2f0eb9fe,0x2d7e3ae9,0x3bf83807,
0x385db534,0xbab5bb91,0x3c0038d8,0xa248ba5e,0x39723bf8,0x39dcad7e,0xb3653900,0x3bc93a3f,0xbb02b115,0x37b73be6,0xbb1abb46,0xb75e36aa,0xb414bb5a,0xbbbcb64e,0x394db1db,0xb9febbdd,
0xbb02bb80,0xb7b73593,0xb75ebbc9,0xbb1ab365,0x38d8b2a1,0xba5ebbd4,0x3b9135f1,0xb534bb6e,0x39963bfc,0x39baabd9,0x31db3ae9,0x3bdd3807,0xba7cad7e,0x38b03bf8,0xbbffb900,0x28b63a3f,
0xb6aa35f1,0x3b463b6e,0xb8b031db,0x3a7c3bdd,0xbb1abb91,0xb75e3534,0xba3fbbed,0xb900304e,0x3807b475,0xbae9bbaf,0x394dad7e,0xb9febbf8,0x3ab53bc9,0x385db365,0x39ba3bff,0x3996a8b6,
0x3b803b5a,0x3593b64e,0x3be63a99,0x3115b887,0xb4d53705,0x3ba03b30,0xaf0e38d8,0x3bf43a5e,0xbbbcbb02,0xb41437b7,0xbbfcba1f,0xabd93927,0x32a1b832,0xbbd4bad0,0x2248b972,0xbc00b9dc,
0x3475b6aa,0xbbafbb46,0xb4d5bad0,0xbba0b832,0x3bed3ab5,0x304eb85d,0x3b30364e,0xb705bb5a,0x2248394d,0x3c0039fe,0x38873bbc,0x3a993414,0xbbe6b927,0x31153a1f,0xb9dcaf0e,0x39723bf4,
0xbbd4bb30,0xb2a13705,0xb9bab04e,0x39963bed,0xa8b6b927,0xbbffba1f,0xbad0bbf4,0xb8322f0e,0x3baf38b0,0xb475ba7c,0x34d5b593,0xbba0bb80,0x38073b6e,0x3ae935f1,0x3bfc3a99,0x2bd9b887,
0xb04e375e,0x3bed3b1a,0x3b913baf,0x3534b475,0xbbd4b972,0x32a139dc,0x224838b0,0x3c003a7c,0xb832bb5a,0xbad0b64e,0xbb80b887,0x35933a99,0x39002bd9,0xba3fbbfc,0xb927bbbc,0xba1fb414,
0x3bfc3b02,0x2bd9b7b7,0xb04eb927,0xbbedba1f,0x35f13a7c,0x3b6e38b0,0x3ab536aa,0xb85dbb46,0xb972b1db,0x39dc3bdd,0x3ad03c00,0x3832a248,0xbba0bbbc,0xb4d53414,0xaf0e3705,0x3bf43b30,
0xa248b807,0xbc00bae9,0xba99b705,0x38873b30,0x3ad037b7,0xb832bb02,0xbb46bbf8,0xb6aa2d7e,0x3b1a3bff,0x375ea8b6,0xaf0eb8b0,0xbbf4ba7c,0x2bd9385d,0x3bfc3ab5,0x3a5e364e,0xb8d8bb5a,
0xbbf8bad0,0x2d7e3832,0x3b023bff,0x37b728b6,0xb94dbb6e,0xb9feb5f1,0x304e3887,0x3bed3a99,0x32a1b414,0xbbd4bbbc,0xb9bab534,0x39963b91,0x3b463900,0xb6aaba3f,0xbbe6bba0,0xb11534d5,
0x3115385d,0x3be63ab5,0x28b6b5f1,0xbbffbb6e,0xb900b414,0x3a3f3bbc,0x3a1f3705,0xb927bb30,0xbbfcbb1a,0x2bd9375e,0x3bed3baf,0x304eb475,0xb9babb80,0xb996b593,0x38873ad0,0x3a993832,
0x3bc93a99,0xb365b887,0xbb46b996,0x36aa39ba,0x3b023bed,0x37b7304e,0xbba0bbfc,0xb4d52bd9,0x35343927,0x3b913a1f,0xb807ba3f,0xbae9b900,0xb64ea8b6,0x3b5a3bff,0x32a1b115,0xbbd4bbe6,
0xb4d5b8b0,0xbba0ba7c,0x3a3f3b80,0x39003593,0x35342248,0xbb91bc00,0x3414385d,0x3bbc3ab5,0x3a9938d8,0xb887ba5e,0xb5f1abd9,0x3b6e3bfc,0x3bff3baf,0x28b6b475,0xbad0b927,0x38323a1f,
0xbb6eba5e,0x35f138d8,0x32a1abd9,0xbbd4bbfc,0xbbe6bbf4,0xb1152f0e,0x3972375e,0xb9dcbb1a,0xba1fbb46,0xb927b6aa,0x3baf3ad0,0xb475b832,0xb534b887,0xbb91ba99,0x3bbc3c00,0x3414a248,
0x37053900,0x3b303a3f,0xbbbcbb1a,0x3414375e,0x22483365,0x3c003bc9,0xbbddbbff,0xb1db28b6,0xb6aab2a1,0x3b463bd4,0xba7cbb5a,0xb8b0b64e,0xba1fb8d8,0x39273a5e,0xb7b7b94d,0xbb02b9fe,
0x3ae93a1f,0xb807b927,0x394d3a3f,0x39fe3900,0x3bdd3b80,0xb1dbb593,0x35f13832,0x3b6e3ad0,0x3be63c00,0x3115a248,0x28b632a1,0x3bff3bd4,0x3b023b91,0x37b73534,0xb4d5b04e,0x3ba03bed,
0xb887b94d,0xba99b9fe,0x35f13414,0xbb6ebbbc,0xb593b75e,0xbb80bb1a,0x38b037b7,0xba7cbb02,0xaf0eb365,0xbbf4bbc9,0x3a1f3972,0xb927b9dc,0x304e2248,0xbbedbc00,0x3b303ab5,0xb705b85d,
0xba3fb9dc,0x39003972,0xbbf8bbe6,0x2d7e3115,0xbae9ba99,0x38073887,0xbbfcbc00,0xabd92248,0xbb6ebb30,0x35f13705,0xbbd4bbed,0xb2a1b04e,0xbbc9bba0,0x336534d5,0xbb80bbaf,0xb593b475,
0x39723996,0x39dc39ba,0x3832385d,0x3ad03ab5,0x3927394d,0x3a1f39fe,0x37b73807,0x3b023ae9,0x38d83900,0x3a5e3a3f,0x3705375e,0x3b303b1a,0x388738b0,0x3a993a7c,0x364e36aa,0x3b5a3b46,
0x36aa3b5a,0x3b46b64e,0x38b03a99,0x3a7cb887,0xb75ebb30,0xbb1a3705,0xb900ba5e,0xba3f38d8,0x38073b02,0x3ae9b7b7,0x394d3a1f,0x39feb927,0xb85dbad0,0xbab53832,0xb996b9dc,0xb9ba3972,
0x3475bb80,0xbbafb593,0xb4d5bbc9,0xbba03365,0xb04e3bd4,0x3bed32a1,0x37053b6e,0x3b30b5f1,0xa248bbfc,0xbc00abd9,0xb887bae9,0xba993807,0x31153bf8,0x3be6ad7e,0x39723a3f,0x39dcb900,
0xbab53705,0x385d3b30,0xa2483bed,0x3c00304e,0x3972b927,0xb9dcba1f,0xb365bbf4,0xbbc92f0e,0xb7b73a7c,0x3b0238b0,0x375e3b80,0x3b1ab593,0x3414bb6e,0xbbbcb5f1,0xb94dba99,0xb9fe3887,
0x3bed34d5,0x304ebba0,0x3534bb02,0xbb91b7b7,0xbbd428b6,0x32a13bff,0x22483be6,0x3c003115,0x3ad0b5f1,0xb832bb6e,0xb593bbdd,0xbb8031db,0xb900394d,0x3a3f39fe,0x39273ae9,0x3a1fb807,
0xb94dbb02,0xb9fe37b7,0xb8d83927,0x3a5e3a1f,0x3b5a38b0,0x364eba7c,0x32a1bb46,0xbbd4b6aa,0xbbffb1db,0x28b63bdd,0x33653c00,0x3bc9a248,0x3b1ab414,0xb75ebbbc,0xb900bb30,0xba3f3705,
0x22483bbc,0x3c003414,0x3a99b534,0xb887bb91,0xb832bbaf,0xbad03475,0xb6aa3a1f,0x3b463927,0x3b1a3972,0x375eb9dc,0xaf0ebbe6,0xbbf4b115,0xbbfcb2a1,0x2bd93bd4,0x38d83b6e,0x3a5eb5f1,
0x3927b832,0xba1fbad0,0xbbafa8b6,0x34753bff,0xabd93b6e,0x3bfc35f1,0x38d8b887,0xba5eba99,0xb85dbbbc,0xbab53414,0xa2483b91,0x3c003534,0x3b803900,0x3593ba3f,0xb8b0bba0,0xba7c34d5,
0xbbe6b2a1,0x31153bd4,0x3bff364e,0x28b6bb5a,0x3900b807,0xba3fbae9,0xba1f3534,0x39273b91,0x2bd93ba0,0x3bfc34d5,0x304ebb02,0xbbedb7b7,0xb9babb46,0xb99636aa,0x38873bc9,0x3a99b365,
0x3ad03a99,0x3832b887,0xbb80b996,0xb59339ba,0xbbafb04e,0x34753bed,0x3b1aabd9,0xb75ebbfc,0x3705b927,0xbb30ba1f,0xb4143a3f,0x3bbc3900,0x35f13bff,0x3b6e28b6,0xb85dbbe6,0xbab53115,
0xb4d5bbe6,0xbba0b115,0x3a3f3b46,0x3900b6aa,0x3b9139ba,0x3534b996,0xbbbcb2a1,0x34143bd4,0xba99304e,0x38873bed,0x35f1b94d,0xbb6eb9fe,0x28b6bb02,0xbbffb7b7,0x38323bf8,0x3ad0ad7e,
0xb64e38d8,0x3b5a3a5e,0xb85dbbfc,0xbab52bd9,0xb8b0bbf4,0xba7c2f0e,0x3bff375e,0xa8b6bb1a,0x3bf836aa,0xad7ebb46,0xb7b73832,0x3b023ad0,0xb7053887,0x3b303a99,0xb807bc00,0xbae92248,
0x3b302f0e,0xb705bbf4,0x34143ba0,0x3bbc34d5,0x22483ad0,0x3c003832,0xbbddb972,0xb1db39dc,0xbb46bab5,0xb6aa385d,0x38b0b5f1,0xba7cbb6e,0x3a1fb04e,0xb927bbed,0x37b73bfc,0x3b022bd9,
0xbbbcba1f,0xb4143927,0x2bd9ba3f,0xbbfcb900,0x3887b593,0xba99bb80,0x3b5a3ad0,0x364eb832,0x38b03c00,0x3a7ca248,0xb97232a1,0x39dc3bd4,0xbbafb534,0x34753b91,0xb75ebbed,0xbb1ab04e,
0x38873bfc,0x3a992bd9,0xb5f13807,0x3b6e3ae9,0xbb80b4d5,0x35933ba0,0xba7cbbaf,0xb8b03475,0xaf0ebad0,0xbbf4b832,0x3a1fa8b6,0xb927bbff,0x3bed39ba,0x304eb996,0x37053bd4,0x3b3032a1,
0x2f0eb972,0xbbf4b9dc,0x3927b115,0xba1fbbe6,0x3bbc3a99,0x3414b887,0x394d3c00,0x39fea248,0xb64e3705,0x3b5a3b30,0xbab5b04e,0x385d3bed,0xbad0bba0,0xb83234d5,0xb6aabbaf,0xbb46b475,
0xb9dca248,0x39723c00,0xbad0b2a1,0x38323bd4,0xb927bbfc,0xba1fabd9,0xb7b7bbbc,0xbb02b414,0x3a5e2f0e,0xb8d8bbf4,0x3b3034d5,0xb705bba0,0x38873be6,0x3a993115,0x364e3b80,0x3b5a3593,
0x3bff3996,0xa8b6b9ba,0x3bc9385d,0xb365bab5,0x2d7e39fe,0x3bf8394d,0x34753ae9,0x3baf3807,0xbbedb900,0x304e3a3f,0xbb91b75e,0x35343b1a,0xb1dbba7c,0xbbddb8b0,0xb5f1bb46,0xbb6eb6aa,
0xba3fbbff,0xb90028b6,0xbbf8ba7c,0xad7e38b0,0x3807b1db,0xbae9bbdd,0xabd9b996,0xbbfcb9ba,0x3b6e3b91,0x35f1b534,0x3bd438d8,0xb2a1ba5e,0xb365375e,0x3bc93b1a,0x35933b02,0x3b8037b7,
0x31db39fe,0x3bdd394d,0x3b5a3bbc,0x364eb414,0xbb46b75e,0x36aa3b1a,0xb11537b7,0x3be63b02,0xb900bbc9,0xba3fb365,0xbbf8b9dc,0x2d7e3972,0x38d8a248,0xba5ebc00,0xb534bab5,0xbb91b85d,
0x3807ad7e,0xbae9bbf8,0xb9febbf4,0xb94daf0e,0x3bdd3b46,0x31dbb6aa,0x35f1b365,0xbb6ebbc9,0x31153996,0x3be639ba,0x3bff3ab5,0x28b6b85d,0xbb02b705,0x37b73b30,0x34d53a5e,0x3ba038d8,
0xbb91b900,0x35343a3f,0x38073b1a,0x3ae9375e,0xb996bbc9,0xb9bab365,0xb887a8b6,0x3a993bff,0x3593b2a1,0xbb80bbd4,0xbbe6bb5a,0xb115364e,0x3bf83a5e,0xad7eb8d8,0xb475b9fe,0xbbafb94d,
0x3b6e3bed,0x35f1b04e,0xb2a1b94d,0xbbd4b9fe,0x31153900,0x3be63a3f,0x39dc34d5,0xb972bba0,0xba1fb593,0x39273b80,0x3baf3bc9,0x3475b365,0xbb91bbdd,0xb53431db,0x34143996,0x3bbc39ba,
0xb75eba7c,0xbb1ab8b0,0xaf0e3593,0x3bf43b80,0x3705a248,0xbb30bc00,0xbae9b85d,0x38073ab5,0x3bdd3a5e,0xb1dbb8d8,0xbb5abbfc,0xb64e2bd9,0x39dc3baf,0x39723475,0xb365b927,0xbbc9ba1f,
0xb36531db,0x3bc93bdd,0x36aa2248,0xbb46bc00,0xbb02b8d8,0x37b73a5e,0x3ba039fe,0xb4d5b94d,0xbb91bbf8,0xb5342d7e,0x3ae93bf4,0x38072f0e,0xb64eb9dc,0xbb5ab972,0x32a138b0,0x3bd43a7c,
0x3a7c385d,0xb8b0bab5,0xb972b5f1,0x39dc3b6e,0x3bf43bbc,0x2f0eb414,0xbbf8bb30,0x2d7e3705,0x394d3b1a,0x39fe375e,0xba5ebbaf,0xb8d8b475,0xa2483593,0x3c003b80,0xb1dbb832,0xbbddbad0,
0xbbf8bbc9,0xad7e3365,0x3b023972,0xb7b7b9dc,0xb9febb5a,0xb94db64e,0x3bed3bdd,0x304eb1db,0xb2a1b807,0xbbd4bae9,0x39ba3b30,0x39963705,0x36aa2f0e,0xbb46bbf4,0x3115375e,0x3be63b1a,
0x39963ae9,0x39ba3807,0xbbddbb30,0x31db3705,0x336537b7,0x3bc93b02,0xbb80bbf8,0xb593ad7e,0xb4d5a8b6,0x3ba03bff,0xb900ba7c,0xba3fb8b0,0xb9feb85d,0x394d3ab5,0xb04eb64e,0xbbedbb5a,
0xabd9b475,0xbbfcbbaf,0x3bed3bf8,0x304ead7e,0x35f13115,0xbb6ebbe6,0x3ab53b80,0x385d3593,0x39dc3887,0xb972ba99,0x38323996,0x3ad039ba,0x3ba03ae9,0xb4d5b807,0x2f0e3534,0x3bf43b91,
0xb8d8b75e,0x3a5e3b1a,0xbb30bbaf,0xb705b475,0xbab5b9dc,0x385d3972,0xb996ba7c,0xb9bab8b0,0xbbc9bb5a,0x3365364e,0xb6aab887,0xbb46ba99,0xbbf4bbfc,0xaf0e2bd9,0xad7eb414,0xbbf8bbbc,
0x3bd43b91,0xb2a1b534,0x39ba3a5e,0x399638d8,0x3bff3bf8,0x28b6ad7e,0x38323900,0x3ad03a3f,0x3baf3be6,0x34753115,0x34d536aa,0x3ba03b46,0x3ae93b5a,0x3807364e,0x2bd931db,0x3bfc3bdd,
0xbb02bb46,0xb7b7b6aa,0xb75eb832,0xbb1abad0,0xba5ebab5,0xb8d8b85d,0xb534b64e,0xbb91bb5a,0xb996b9fe,0xb9bab94d,0xb1dbb414,0xbbddbbbc,0xb8b0b927,0xba7cba1f,0xa8b6af0e,0xbbffbbf4,
0x359335f1,0x3b803b6e,0x311531db,0x3be63bdd,0x34d53534,0x3ba03b91,0x2f0e304e,0x3bf43bed,0x34143475,0x3bbc3baf,0x2bd92d7e,0x3bfc3bf8,0x32a13365,0x3bd43bc9,0x224828b6,0x3c003bff,
0x40000,0x60002,0xc0008,0xe000a,0x380034,0x3a0036,0x40003c,0x42003e,0x6c0068,0x6e006a,0x740070,0x760072,0xa0009c,0xa2009e,0xa800a4,0xaa00a6,
0xd400d0,0xd600d2,0xdc00d8,0xde00da,0x1080104,0x10a0106,0x110010c,0x112010e,0x13c0138,0x13e013a,0x1440140,0x1460142,0x170016c,0x172016e,0x1780174,0x17a0176,
0x1a401a0,0x1a601a2,0x1ac01a8,0x1ae01aa,0x1d801d4,0x1da01d6,0x1e001dc,0x1e201de,0x20c0208,0x20e020a,0x2140210,0x2160212,0x240023c,0x242023e,0x2480244,0x24a0246,
0x2740270,0x2760272,0x27c0278,0x27e027a,0x2a802a4,0x2aa02a6,0x2b002ac,0x2b202ae,0x2dc02d8,0x2de02da,0x2e402e0,0x2e602e2,0x310030c,0x312030e,0x3180314,0x31a0316,
0x3440340,0x3460342,0x34c0348,0x34e034a,0x3780374,0x37a0376,0x380037c,0x382037e,0x3ac03a8,0x3ae03aa,0x3b403b0,0x3b603b2,0x3e003dc,0x3e203de,0x3e803e4,0x3ea03e6,
0x4140410,0x4160412,0x41c0418,0x41e041a,0x4480444,0x44a0446,0x450044c,0x452044e,0x47c0478,0x47e047a,0x4840480,0x4860482,0x4b004ac,0x4b204ae,0x4b804b4,0x4ba04b6,
0x4e404e0,0x4e604e2,0x4ec04e8,0x4ee04ea,0x5180514,0x51a0516,0x520051c,0x522051e,0x54c0548,0x54e054a,0x5540550,0x5560552,0x580057c,0x582057e,0x5880584,0x58a0586,
0x5b405b0,0x5b605b2,0x5bc05b8,0x5be05ba,0x5e805e4,0x5ea05e6,0x5f005ec,0x5f205ee,0x61c0618,0x61e061a,0x6240620,0x6260622,0x650064c,0x652064e,0x6580654,0x65a0656,
0x140010,0x160012,0x120010,0x440012,0x480044,0x4a0046,0x460044,0x780046,0x7c0078,0x7e007a,0x7a0078,0xac007a,0xb000ac,0xb200ae,0xae00ac,0xe000ae,
0xe400e0,0xe600e2,0xe200e0,0x11400e2,0x1180114,0x11a0116,0x1160114,0x1480116,0x14c0148,0x14e014a,0x14a0148,0x17c014a,0x180017c,0x182017e,0x17e017c,0x1b0017e,
0x1b401b0,0x1b601b2,0x1b201b0,0x1e401b2,0x1e801e4,0x1ea01e6,0x1e601e4,0x21801e6,0x21c0218,0x21e021a,0x21a0218,0x24c021a,0x250024c,0x252024e,0x24e024c,0x280024e,
0x2840280,0x2860282,0x2820280,0x2b40282,0x2b802b4,0x2ba02b6,0x2b602b4,0x2e802b6,0x2ec02e8,0x2ee02ea,0x2ea02e8,0x31c02ea,0x320031c,0x322031e,0x31e031c,0x350031e,
0x3540350,0x3560352,0x3520350,0x3840352,0x3880384,0x38a0386,0x3860384,0x3b80386,0x3bc03b8,0x3be03ba,0x3ba03b8,0x3ec03ba,0x3f003ec,0x3f203ee,0x3ee03ec,0x42003ee,
0x4240420,0x4260422,0x4220420,0x4540422,0x4580454,0x45a0456,0x4560454,0x4880456,0x48c0488,0x48e048a,0x48a0488,0x4bc048a,0x4c004bc,0x4c204be,0x4be04bc,0x4f004be,
0x4f404f0,0x4f604f2,0x4f204f0,0x52404f2,0x5280524,0x52a0526,0x5260524,0x5580526,0x55c0558,0x55e055a,0x55a0558,0x58c055a,0x590058c,0x592058e,0x58e058c,0x5c0058e,
0x5c405c0,0x5c605c2,0x5c205c0,0x5f405c2,0x5f805f4,0x5fa05f6,0x5f605f4,0x62805f6,0x62c0628,0x62e062a,0x62a0628,0x65c062a,0x660065c,0x662065e,0x65e065c,0x18065e,
0x180018,0x4c001a,0x1a0018,0x4c001a,0x4c004c,0x80004e,0x4e004c,0x80004e,0x800080,0xb40082,0x820080,0xb40082,0xb400b4,0xe800b6,0xb600b4,0xe800b6,
0xe800e8,0x11c00ea,0xea00e8,0x11c00ea,0x11c011c,0x150011e,0x11e011c,0x150011e,0x1500150,0x1840152,0x1520150,0x1840152,0x1840184,0x1b80186,0x1860184,0x1b80186,
0x1b801b8,0x1ec01ba,0x1ba01b8,0x1ec01ba,0x1ec01ec,0x22001ee,0x1ee01ec,0x22001ee,0x2200220,0x2540222,0x2220220,0x2540222,0x2540254,0x2880256,0x2560254,0x2880256,
0x2880288,0x2bc028a,0x28a0288,0x2bc028a,0x2bc02bc,0x2f002be,0x2be02bc,0x2f002be,0x2f002f0,0x32402f2,0x2f202f0,0x32402f2,0x3240324,0x3580326,0x3260324,0x3580326,
0x3580358,0x38c035a,0x35a0358,0x38c035a,0x38c038c,0x3c0038e,0x38e038c,0x3c0038e,0x3c003c0,0x3f403c2,0x3c203c0,0x3f403c2,0x3f403f4,0x42803f6,0x3f603f4,0x42803f6,
0x4280428,0x45c042a,0x42a0428,0x45c042a,0x45c045c,0x490045e,0x45e045c,0x490045e,0x4900490,0x4c40492,0x4920490,0x4c40492,0x4c404c4,0x4f804c6,0x4c604c4,0x4f804c6,
0x4f804f8,0x52c04fa,0x4fa04f8,0x52c04fa,0x52c052c,0x560052e,0x52e052c,0x560052e,0x5600560,0x5940562,0x5620560,0x5940562,0x5940594,0x5c80596,0x5960594,0x5c80596,
0x5c805c8,0x5fc05ca,0x5ca05c8,0x5fc05ca,0x5fc05fc,0x63005fe,0x5fe05fc,0x63005fe,0x6300630,0x6640632,0x6320630,0x6640632,0x6640664,0x1c0666,0x6660664,0x1c0666,
0x1c001c,0x50001e,0x1e001c,0x50001e,0x500050,0x840052,0x520050,0x840052,0x840084,0xb80086,0x860084,0xb80086,0xb800b8,0xec00ba,0xba00b8,0xec00ba,
0xec00ec,0x12000ee,0xee00ec,0x12000ee,0x1200120,0x1540122,0x1220120,0x1540122,0x1540154,0x1880156,0x1560154,0x1880156,0x1880188,0x1bc018a,0x18a0188,0x1bc018a,
0x1bc01bc,0x1f001be,0x1be01bc,0x1f001be,0x1f001f0,0x22401f2,0x1f201f0,0x22401f2,0x2240224,0x2580226,0x2260224,0x2580226,0x2580258,0x28c025a,0x25a0258,0x28c025a,
0x28c028c,0x2c0028e,0x28e028c,0x2c0028e,0x2c002c0,0x2f402c2,0x2c202c0,0x2f402c2,0x2f402f4,0x32802f6,0x2f602f4,0x32802f6,0x3280328,0x35c032a,0x32a0328,0x35c032a,
0x35c035c,0x390035e,0x35e035c,0x390035e,0x3900390,0x3c40392,0x3920390,0x3c40392,0x3c403c4,0x3f803c6,0x3c603c4,0x3f803c6,0x3f803f8,0x42c03fa,0x3fa03f8,0x42c03fa,
0x42c042c,0x460042e,0x42e042c,0x460042e,0x4600460,0x4940462,0x4620460,0x4940462,0x4940494,0x4c80496,0x4960494,0x4c80496,0x4c804c8,0x4fc04ca,0x4ca04c8,0x4fc04ca,
0x4fc04fc,0x53004fe,0x4fe04fc,0x53004fe,0x5300530,0x5640532,0x5320530,0x5640532,0x5640564,0x5980566,0x5660564,0x5980566,0x5980598,0x5cc059a,0x59a0598,0x5cc059a,
0x5cc05cc,0x60005ce,0x5ce05cc,0x60005ce,0x6000600,0x6340602,0x6020600,0x6340602,0x6340634,0x6680636,0x6360634,0x6680636,0x6680668,0x20066a,0x66a0668,0x20066a,
0x5d605d6,0x60a05d6,0x5d605d6,0x60a060a,0x60a060a,0x63e063e,0x60a060a,0x63e063e,0x63e063e,0x672063e,0x63e063e,0x6720672,0x6720672,0x280028,0x6720672,0x280028,
0x5060506,0x53a0506,0x5060506,0x53a053a,0x53a053a,0x56e056e,0x53a053a,0x56e056e,0x56e056e,0x5a2056e,0x56e056e,0x5a205a2,0x5a205a2,0x5d605d6,0x5a205a2,0x5d605d6,
0x4360436,0x46a0436,0x4360436,0x46a046a,0x46a046a,0x49e049e,0x46a046a,0x49e049e,0x49e049e,0x4d2049e,0x49e049e,0x4d204d2,0x4d204d2,0x5060506,0x4d204d2,0x5060506,
0x3660366,0x39a0366,0x3660366,0x39a039a,0x39a039a,0x3ce03ce,0x39a039a,0x3ce03ce,0x3ce03ce,0x40203ce,0x3ce03ce,0x4020402,0x4020402,0x4360436,0x4020402,0x4360436,
0x2960296,0x2ca0296,0x2960296,0x2ca02ca,0x2ca02ca,0x2fe02fe,0x2ca02ca,0x2fe02fe,0x2fe02fe,0x33202fe,0x2fe02fe,0x3320332,0x3320332,0x3660366,0x3320332,0x3660366,
0x1c601c6,0x1fa01c6,0x1c601c6,0x1fa01fa,0x1fa01fa,0x22e022e,0x1fa01fa,0x22e022e,0x22e022e,0x262022e,0x22e022e,0x2620262,0x2620262,0x2960296,0x2620262,0x2960296,
0xf600f6,0x12a00f6,0xf600f6,0x12a012a,0x12a012a,0x15e015e,0x12a012a,0x15e015e,0x15e015e,0x192015e,0x15e015e,0x1920192,0x1920192,0x1c601c6,0x1920192,0x1c601c6,
0x260026,0x5a0026,0x260026,0x5a005a,0x5a005a,0x8e008e,0x5a005a,0x8e008e,0x8e008e,0xc2008e,0x8e008e,0xc200c2,0xc200c2,0xf600f6,0xc200c2,0xf600f6,
0x5d405d4,0x60805d4,0x5d405d4,0x6080608,0x6080608,0x63c063c,0x6080608,0x63c063c,0x63c063c,0x670063c,0x63c063c,0x6700670,0x6700670,0x260026,0x6700670,0x260026,
0x5040504,0x5380504,0x5040504,0x5380538,0x5380538,0x56c056c,0x5380538,0x56c056c,0x56c056c,0x5a0056c,0x56c056c,0x5a005a0,0x5a005a0,0x5d405d4,0x5a005a0,0x5d405d4,
0x4340434,0x4680434,0x4340434,0x4680468,0x4680468,0x49c049c,0x4680468,0x49c049c,0x49c049c,0x4d0049c,0x49c049c,0x4d004d0,0x4d004d0,0x5040504,0x4d004d0,0x5040504,
0x3640364,0x3980364,0x3640364,0x3980398,0x3980398,0x3cc03cc,0x3980398,0x3cc03cc,0x3cc03cc,0x40003cc,0x3cc03cc,0x4000400,0x4000400,0x4340434,0x4000400,0x4340434,
0x2940294,0x2c80294,0x2940294,0x2c802c8,0x2c802c8,0x2fc02fc,0x2c802c8,0x2fc02fc,0x2fc02fc,0x33002fc,0x2fc02fc,0x3300330,0x3300330,0x3640364,0x3300330,0x3640364,
0x1c401c4,0x1f801c4,0x1c401c4,0x1f801f8,0x1f801f8,0x22c022c,0x1f801f8,0x22c022c,0x22c022c,0x260022c,0x22c022c,0x2600260,0x2600260,0x2940294,0x2600260,0x2940294,
0xf400f4,0x12800f4,0xf400f4,0x1280128,0x1280128,0x15c015c,0x1280128,0x15c015c,0x15c015c,0x190015c,0x15c015c,0x1900190,0x1900190,0x1c401c4,0x1900190,0x1c401c4,
0x240024,0x580024,0x240024,0x580058,0x580058,0x8c008c,0x580058,0x8c008c,0x8c008c,0xc0008c,0x8c008c,0xc000c0,0xc000c0,0xf400f4,0xc000c0,0xf400f4,
0x5d205d2,0x60605d2,0x5d205d2,0x6060606,0x6060606,0x63a063a,0x6060606,0x63a063a,0x63a063a,0x66e063a,0x63a063a,0x66e066e,0x66e066e,0x240024,0x66e066e,0x240024,
0x5020502,0x5360502,0x5020502,0x5360536,0x5360536,0x56a056a,0x5360536,0x56a056a,0x56a056a,0x59e056a,0x56a056a,0x59e059e,0x59e059e,0x5d205d2,0x59e059e,0x5d205d2,
0x4320432,0x4660432,0x4320432,0x4660466,0x4660466,0x49a049a,0x4660466,0x49a049a,0x49a049a,0x4ce049a,0x49a049a,0x4ce04ce,0x4ce04ce,0x5020502,0x4ce04ce,0x5020502,
0x3620362,0x3960362,0x3620362,0x3960396,0x3960396,0x3ca03ca,0x3960396,0x3ca03ca,0x3ca03ca,0x3fe03ca,0x3ca03ca,0x3fe03fe,0x3fe03fe,0x4320432,0x3fe03fe,0x4320432,
0x2920292,0x2c60292,0x2920292,0x2c602c6,0x2c602c6,0x2fa02fa,0x2c602c6,0x2fa02fa,0x2fa02fa,0x32e02fa,0x2fa02fa,0x32e032e,0x32e032e,0x3620362,0x32e032e,0x3620362,
0x1c201c2,0x1f601c2,0x1c201c2,0x1f601f6,0x1f601f6,0x22a022a,0x1f601f6,0x22a022a,0x22a022a,0x25e022a,0x22a022a,0x25e025e,0x25e025e,0x2920292,0x25e025e,0x2920292,
0xf200f2,0x12600f2,0xf200f2,0x1260126,0x1260126,0x15a015a,0x1260126,0x15a015a,0x15a015a,0x18e015a,0x15a015a,0x18e018e,0x18e018e,0x1c201c2,0x18e018e,0x1c201c2,
0x220022,0x560022,0x220022,0x560056,0x560056,0x8a008a,0x560056,0x8a008a,0x8a008a,0xbe008a,0x8a008a,0xbe00be,0xbe00be,0xf200f2,0xbe00be,0xf200f2,
0x5d005d0,0x60405d0,0x5d005d0,0x6040604,0x6040604,0x6380638,0x6040604,0x6380638,0x6380638,0x66c0638,0x6380638,0x66c066c,0x66c066c,0x220022,0x66c066c,0x220022,
0x5000500,0x5340500,0x5000500,0x5340534,0x5340534,0x5680568,0x5340534,0x5680568,0x5680568,0x59c0568,0x5680568,0x59c059c,0x59c059c,0x5d005d0,0x59c059c,0x5d005d0,
0x4300430,0x4640430,0x4300430,0x4640464,0x4640464,0x4980498,0x4640464,0x4980498,0x4980498,0x4cc0498,0x4980498,0x4cc04cc,0x4cc04cc,0x5000500,0x4cc04cc,0x5000500,
0x3600360,0x3940360,0x3600360,0x3940394,0x3940394,0x3c803c8,0x3940394,0x3c803c8,0x3c803c8,0x3fc03c8,0x3c803c8,0x3fc03fc,0x3fc03fc,0x4300430,0x3fc03fc,0x4300430,
0x2900290,0x2c40290,0x2900290,0x2c402c4,0x2c402c4,0x2f802f8,0x2c402c4,0x2f802f8,0x2f802f8,0x32c02f8,0x2f802f8,0x32c032c,0x32c032c,0x3600360,0x32c032c,0x3600360,
0x1c001c0,0x1f401c0,0x1c001c0,0x1f401f4,0x1f401f4,0x2280228,0x1f401f4,0x2280228,0x2280228,0x25c0228,0x2280228,0x25c025c,0x25c025c,0x2900290,0x25c025c,0x2900290,
0xf000f0,0x12400f0,0xf000f0,0x1240124,0x1240124,0x1580158,0x1240124,0x1580158,0x1580158,0x18c0158,0x1580158,0x18c018c,0x18c018c,0x1c001c0,0x18c018c,0x1c001c0,
0x200020,0x540020,0x200020,0x540054,0x540054,0x880088,0x540054,0x880088,0x880088,0xbc0088,0x880088,0xbc00bc,0xbc00bc,0xf000f0,0xbc00bc,0xf000f0,
0x30003000,0x30003000,0x30003000,0x30003000,0x30003000,0x30003000,0x30003000,0x30003000,0x0,0x0,0x0,0x0,0x0,0x0,0x0,0x0,
0x30003000,0x30003000,0x30003000,0x30003000,0x30003000,0x30003000,0x30003000,0x30003000,0x0,0x0,0x0,0x0,0x0,0x0,0x0,0x0,
0x2a1f2da8,0xaf64ada8,0xaa1fada8,0x2f642da8,0x2f643000,0xaa1f0000,0xaf64b000,0x2a1f8000,0x2f642da8,0x2a1f2da8,0xaf64ada8,0xaa1fada8,0x2a1f0000,0x2f643000,0xaa1f0000,0xaf64b000,
0x263e2c72,0xafd9aea7,0xa63eac72,0x2fd92ea7,0x2ea72fd9,0xac72a63e,0xaea7afd9,0x2c72263e,0x2fd92ea7,0x263e2c72,0xafd9aea7,0xa63eac72,0x2c72263e,0x2ea72fd9,0xac72a63e,0xaea7afd9,
0x2da80000,0xada80000,0x2da88000,0xada80000,0x2da83000,0xada8b000,0x2da83000,0xada8b000,0x2da83000,0xada8b000,0x2da83000,0xada8b000,0xada80000,0x2da88000,0xada80000,0x2da88000,
0x2f642a1f,0xaf64aa1f,0x2f642a1f,0xaf64aa1f,0x2a1f2f64,0xaa1faf64,0x2a1f2f64,0xaa1faf64,0x2a1f2f64,0xaa1faf64,0x2a1f2f64,0xaa1faf64,0xaf64aa1f,0x2f642a1f,0xaf64aa1f,0x2f642a1f,
0xaa1f2da8,0x2f642da8,0x2a1fada8,0xaf64ada8,0x2f640000,0xaa1fb000,0xaf640000,0x2a1f3000,0xaf64ada8,0xaa1f2da8,0x2f642da8,0x2a1fada8,0x2a1f3000,0x2f648000,0xaa1fb000,0xaf640000,
0xaea7263e,0x2c722fd9,0x2ea7a63e,0xac72afd9,0x2fd92c72,0x263eaea7,0xafd9ac72,0xa63e2ea7,0xac72afd9,0xaea7263e,0x2c722fd9,0x2ea7a63e,0xa63e2ea7,0x2fd92c72,0x263eaea7,0xafd9ac72,
0xada82da8,0xada82da8,0xada82da8,0xada82da8,0x2da8ada8,0x2da8ada8,0x2da8ada8,0x2da8ada8,0x2da82da8,0x2da82da8,0x2da82da8,0x2da82da8,0xada8ada8,0xada8ada8,0xada8ada8,0xada8ada8,
0x3000,0x3000,0x3000,0x80003000,0x8000b000,0x8000b000,0x8000b000,0x8000b000,0x30000000,0x30008000,0x30008000,0x30008000,0xb0000000,0xb0000000,0xb0000000,0xb0000000,
0x2ea7263e,0xac722fd9,0xaea7a63e,0x2c72afd9,0xafd92c72,0xa63eaea7,0x2fd9ac72,0x263e2ea7,0x2c72afd9,0x2ea7263e,0xac722fd9,0xaea7a63e,0x263e2ea7,0xafd92c72,0xa63eaea7,0x2fd9ac72,
0x2f64ada8,0x2a1f2da8,0xaf642da8,0xaa1fada8,0xaa1f3000,0xaf640000,0x2a1fb000,0x2f648000,0xaa1fada8,0x2f64ada8,0x2a1f2da8,0xaf642da8,0x2f640000,0xaa1f3000,0xaf640000,0x2a1fb000,
0xaa1f2f64,0x2a1faf64,0xaa1f2f64,0x2a1faf64,0x2f64aa1f,0xaf642a1f,0x2f64aa1f,0xaf642a1f,0xaf642a1f,0x2f64aa1f,0xaf642a1f,0x2f64aa1f,0xaa1f2f64,0x2a1faf64,0xaa1f2f64,0x2a1faf64,
0x2da80000,0xada80000,0x2da88000,0xada80000,0x2da8b000,0xada83000,0x2da8b000,0xada83000,0xada83000,0x2da8b000,0xada83000,0x2da8b000,0x2da88000,0xada80000,0x2da88000,0xada88000,
0xa63e2c72,0x2fd9aea7,0x263eac72,0xafd92ea7,0xaea72fd9,0x2c72a63e,0x2ea7afd9,0xac72263e,0xafd92ea7,0xa63e2c72,0x2fd9aea7,0x263eac72,0xac72263e,0xaea72fd9,0x2c72a63e,0x2ea7afd9,
0x2f64ada8,0x2a1fada8,0xaf642da8,0xaa1f2da8,0x2a1f0000,0x2f64b000,0xaa1f0000,0xaf643000,0xaa1f2da8,0x2f64ada8,0x2a1fada8,0xaf642da8,0xaf643000,0x2a1f8000,0x2f64b000,0xaa1f8000,
0xb0003000,0xb0003000,0xb0003000,0xb0003000,0xb0003000,0xb0003000,0xb0003000,0xb0003000,0x0,0x8000,0x8000,0x80008000,0x8000,0x8000,0x8000,0x8000,
0x80000000,0x80000000,0x80008000,0x80008000,0x80000000,0x80008000,0x80008000,0x80008000,0xb0003000,0xb0003000,0xb0003000,0xb0003000,0xb0003000,0xb0003000,0xb0003000,0xb0003000,
0xaa1f2da8,0x2f64ada8,0x2a1fada8,0xaf642da8,0xaf643000,0x2a1f0000,0x2f64b000,0xaa1f8000,0xaf642da8,0xaa1f2da8,0x2f64ada8,0x2a1fada8,0xaa1f0000,0xaf643000,0x2a1f0000,0x2f64b000,
0x2fd9aea7,0x263eac72,0xafd92ea7,0xa63e2c72,0x2c72a63e,0x2ea7afd9,0xac72263e,0xaea72fd9,0xa63e2c72,0x2fd9aea7,0x263eac72,0xafd92ea7,0xaea72fd9,0x2c72a63e,0x2ea7afd9,0xac72263e,
0xada80000,0x2da80000,0xada88000,0x2da80000,0xada83000,0x2da8b000,0xada83000,0x2da8b000,0xada83000,0x2da8b000,0xada83000,0x2da8b000,0x2da80000,0xada88000,0x2da88000,0xada88000,
0xaa1f2f64,0x2a1faf64,0xaa1f2f64,0x2a1faf64,0x2f64aa1f,0xaf642a1f,0x2f64aa1f,0xaf642a1f,0x2f64aa1f,0xaf642a1f,0x2f64aa1f,0xaf642a1f,0x2a1faf64,0xaa1f2f64,0x2a1faf64,0xaa1f2f64,
0x2a1f2da8,0xaf642da8,0xaa1fada8,0x2f64ada8,0xaf640000,0x2a1fb000,0x2f640000,0xaa1f3000,0x2f64ada8,0x2a1f2da8,0xaf642da8,0xaa1fada8,0xaa1f3000,0xaf648000,0x2a1fb000,0x2f640000,
0x2c72afd9,0x2ea7263e,0xac722fd9,0xaea7a63e,0x263e2ea7,0xafd92c72,0xa63eaea7,0x2fd9ac72,0xaea7a63e,0x2c72afd9,0x2ea7263e,0xac722fd9,0x2fd9ac72,0x263e2ea7,0xafd92c72,0xa63eaea7,
0x2da8ada8,0x2da8ada8,0x2da8ada8,0x2da8ada8,0xada82da8,0xada82da8,0xada82da8,0xada82da8,0x2da82da8,0x2da82da8,0x2da82da8,0x2da82da8,0xada8ada8,0xada8ada8,0xada8ada8,0xada8ada8,
0x80003000,0x80003000,0x80003000,0x3000,0xb000,0x8000b000,0xb000,0xb000,0xb0000000,0xb0008000,0xb0008000,0xb0008000,0x30000000,0x30000000,0x30000000,0x30008000,
0x2c722fd9,0x2ea7a63e,0xac72afd9,0xaea7263e,0x263eaea7,0xafd9ac72,0xa63e2ea7,0x2fd92c72,0xaea7263e,0x2c722fd9,0x2ea7a63e,0xac72afd9,0x2fd92c72,0x263eaea7,0xafd9ac72,0xa63e2ea7,
0xaf64ada8,0xaa1f2da8,0x2f642da8,0x2a1fada8,0x2a1f3000,0x2f648000,0xaa1fb000,0xaf648000,0x2a1fada8,0xaf64ada8,0xaa1f2da8,0x2f642da8,0xaf640000,0x2a1f3000,0x2f648000,0xaa1fb000,
0x2f642a1f,0xaf64aa1f,0x2f642a1f,0xaf64aa1f,0x2a1f2f64,0xaa1faf64,0x2a1f2f64,0xaa1faf64,0xaa1faf64,0x2a1f2f64,0xaa1faf64,0x2a1f2f64,0x2f642a1f,0xaf64aa1f,0x2f642a1f,0xaf64aa1f,
0xada80000,0x2da80000,0xada88000,0x2da88000,0xada8b000,0x2da83000,0xada8b000,0x2da83000,0x2da83000,0xada8b000,0x2da83000,0xada8b000,0xada88000,0x2da88000,0xada88000,0x2da80000,
0x2fd92ea7,0x263e2c72,0xafd9aea7,0xa63eac72,0x2c72263e,0x2ea72fd9,0xac72a63e,0xaea7afd9,0xa63eac72,0x2fd92ea7,0x263e2c72,0xafd9aea7,0xaea7afd9,0x2c72263e,0x2ea72fd9,0xac72a63e,
0xaf64ada8,0xaa1fada8,0x2f642da8,0x2a1f2da8,0xaa1f0000,0xaf64b000,0x2a1f0000,0x2f643000,0x2a1f2da8,0xaf64ada8,0xaa1fada8,0x2f642da8,0x2f643000,0xaa1f8000,0xaf64b000,0x2a1f0000,
0x80008000,0x80008000,0x80008000,0x80008000,0x80008000,0x80008000,0x80008000,0x80008000,0x30003000,0x30003000,0x30003000,0x30003000,0x30003000,0x30003000,0x30003000,0x30003000,
0x80008000,0x80008000,0x80008000,0x80008000,0x80008000,0x80008000,0x80008000,0x80008000,0x30003000,0x30003000,0x30003000,0x30003000,0x30003000,0x30003000,0x30003000,0x30003000,
0xaf64ada8,0xaa1fada8,0x2f642da8,0x2a1f2da8,0xaa1f8000,0xaf64b000,0x2a1f8000,0x2f643000,0x2a1f2da8,0xaf64ada8,0xaa1fada8,0x2f642da8,0x2f643000,0xaa1f0000,0xaf64b000,0x2a1f8000,
0xafd9aea7,0xa63eac72,0x2fd92ea7,0x263e2c72,0xac72a63e,0xaea7afd9,0x2c72263e,0x2ea72fd9,0x263e2c72,0xafd9aea7,0xa63eac72,0x2fd92ea7,0x2ea72fd9,0xac72a63e,0xaea7afd9,0x2c72263e,
0x2da83000,0xada8b000,0x2da83000,0xada8b000,0xada80000,0x2da88000,0xada80000,0x2da88000,0xada88000,0x2da88000,0xada80000,0x2da88000,0xada8b000,0x2da83000,0xada8b000,0x2da83000,
0x2a1f2f64,0xaa1faf64,0x2a1f2f64,0xaa1faf64,0xaf64aa1f,0x2f642a1f,0xaf64aa1f,0x2f642a1f,0xaf64aa1f,0x2f642a1f,0xaf64aa1f,0x2f642a1f,0xaa1faf64,0x2a1f2f64,0xaa1faf64,0x2a1f2f64,
0xaf64ada8,0xaa1f2da8,0x2f642da8,0x2a1fada8,0x2a1f3000,0x2f648000,0xaa1fb000,0xaf640000,0x2a1fada8,0xaf64ada8,0xaa1f2da8,0x2f642da8,0xaf648000,0x2a1f3000,0x2f648000,0xaa1fb000,
0xac72afd9,0xaea7263e,0x2c722fd9,0x2ea7a63e,0xa63e2ea7,0x2fd92c72,0x263eaea7,0xafd9ac72,0x2ea7a63e,0xac72afd9,0xaea7263e,0x2c722fd9,0xafd9ac72,0xa63e2ea7,0x2fd92c72,0x263eaea7,
0xada8ada8,0xada8ada8,0xada8ada8,0xada8ada8,0x2da82da8,0x2da82da8,0x2da82da8,0x2da82da8,0xada82da8,0xada82da8,0xada82da8,0xada82da8,0x2da8ada8,0x2da8ada8,0x2da8ada8,0x2da8ada8,
0xb0008000,0xb0000000,0xb0000000,0xb0000000,0x30008000,0x30008000,0x30008000,0x30008000,0x3000,0x3000,0x3000,0x80003000,0x8000b000,0x8000b000,0x8000b000,0x8000b000,
0xac722fd9,0xaea7a63e,0x2c72afd9,0x2ea7263e,0xa63eaea7,0x2fd9ac72,0x263e2ea7,0xafd92c72,0x2ea7263e,0xac722fd9,0xaea7a63e,0x2c72afd9,0xafd92c72,0xa63eaea7,0x2fd9ac72,0x263e2ea7,
0x2a1f2da8,0xaf642da8,0xaa1fada8,0x2f64ada8,0xaf648000,0x2a1fb000,0x2f648000,0xaa1f3000,0x2f64ada8,0x2a1f2da8,0xaf642da8,0xaa1fada8,0xaa1f3000,0xaf640000,0x2a1fb000,0x2f648000,
0xaf642a1f,0x2f64aa1f,0xaf642a1f,0x2f64aa1f,0xaa1f2f64,0x2a1faf64,0xaa1f2f64,0x2a1faf64,0x2a1faf64,0xaa1f2f64,0x2a1faf64,0xaa1f2f64,0xaf642a1f,0x2f64aa1f,0xaf642a1f,0x2f64aa1f,
0xada83000,0x2da8b000,0xada83000,0x2da8b000,0x2da88000,0xada80000,0x2da88000,0xada88000,0xada88000,0x2da88000,0xada80000,0x2da88000,0xada83000,0x2da8b000,0xada83000,0x2da8b000,
0xafd92ea7,0xa63e2c72,0x2fd9aea7,0x263eac72,0xac72263e,0xaea72fd9,0x2c72a63e,0x2ea7afd9,0x263eac72,0xafd92ea7,0xa63e2c72,0x2fd9aea7,0x2ea7afd9,0xac72263e,0xaea72fd9,0x2c72a63e,
0xaa1f2da8,0x2f64ada8,0x2a1fada8,0xaf642da8,0xaf643000,0x2a1f8000,0x2f64b000,0xaa1f8000,0xaf642da8,0xaa1f2da8,0x2f64ada8,0x2a1fada8,0xaa1f8000,0xaf643000,0x2a1f8000,0x2f64b000,
0x80008000,0x80000000,0x80000000,0x0,0x80000000,0x80000000,0x80000000,0x80000000,0xb0003000,0xb0003000,0xb0003000,0xb0003000,0xb0003000,0xb0003000,0xb0003000,0xb0003000,
0x3000b000,0x3000b000,0x3000b000,0x3000b000,0x3000b000,0x3000b000,0x3000b000,0x3000b000,0x80000000,0x80000000,0x80008000,0x80008000,0x80000000,0x80008000,0x80008000,0x80008000,
0x2f64ada8,0x2a1fada8,0xaf642da8,0xaa1f2da8,0x2a1f8000,0x2f64b000,0xaa1f8000,0xaf643000,0xaa1f2da8,0x2f64ada8,0x2a1fada8,0xaf642da8,0xaf643000,0x2a1f0000,0x2f64b000,0xaa1f8000,
0x263eac72,0xafd92ea7,0xa63e2c72,0x2fd9aea7,0x2ea7afd9,0xac72263e,0xaea72fd9,0x2c72a63e,0x2fd9aea7,0x263eac72,0xafd92ea7,0xa63e2c72,0x2c72a63e,0x2ea7afd9,0xac72263e,0xaea72fd9,
0xada83000,0x2da8b000,0xada83000,0x2da8b000,0x2da80000,0xada88000,0x2da88000,0xada88000,0x2da88000,0xada88000,0x2da80000,0xada88000,0x2da8b000,0xada83000,0x2da8b000,0xada83000,
0x2f64aa1f,0xaf642a1f,0x2f64aa1f,0xaf642a1f,0x2a1faf64,0xaa1f2f64,0x2a1faf64,0xaa1f2f64,0x2a1faf64,0xaa1f2f64,0x2a1faf64,0xaa1f2f64,0xaf642a1f,0x2f64aa1f,0xaf642a1f,0x2f64aa1f,
0x2f64ada8,0x2a1f2da8,0xaf642da8,0xaa1fada8,0xaa1f3000,0xaf648000,0x2a1fb000,0x2f640000,0xaa1fada8,0x2f64ada8,0x2a1f2da8,0xaf642da8,0x2f648000,0xaa1f3000,0xaf648000,0x2a1fb000,
0xaea7a63e,0x2c72afd9,0x2ea7263e,0xac722fd9,0x2fd9ac72,0x263e2ea7,0xafd92c72,0xa63eaea7,0xac722fd9,0xaea7a63e,0x2c72afd9,0x2ea7263e,0xa63eaea7,0x2fd9ac72,0x263e2ea7,0xafd92c72,
0xada8ada8,0xada8ada8,0xada8ada8,0xada8ada8,0x2da82da8,0x2da82da8,0x2da82da8,0x2da82da8,0x2da8ada8,0x2da8ada8,0x2da8ada8,0x2da8ada8,0xada82da8,0xada82da8,0xada82da8,0xada82da8,
0x30008000,0x30000000,0x30000000,0x30000000,0xb0008000,0xb0008000,0xb0008000,0xb0000000,0x80003000,0x80003000,0x80003000,0x3000,0xb000,0x8000b000,0xb000,0xb000,
0x2ea7a63e,0xac72afd9,0xaea7263e,0x2c722fd9,0xafd9ac72,0xa63e2ea7,0x2fd92c72,0x263eaea7,0x2c722fd9,0x2ea7a63e,0xac72afd9,0xaea7263e,0x263eaea7,0xafd9ac72,0xa63e2ea7,0x2fd92c72,
0xaa1f2da8,0x2f642da8,0x2a1fada8,0xaf64ada8,0x2f648000,0xaa1fb000,0xaf640000,0x2a1f3000,0xaf64ada8,0xaa1f2da8,0x2f642da8,0x2a1fada8,0x2a1f3000,0x2f648000,0xaa1fb000,0xaf648000,
0xaa1faf64,0x2a1f2f64,0xaa1faf64,0x2a1f2f64,0x2f642a1f,0xaf64aa1f,0x2f642a1f,0xaf64aa1f,0xaf64aa1f,0x2f642a1f,0xaf64aa1f,0x2f642a1f,0xaa1faf64,0x2a1f2f64,0xaa1faf64,0x2a1f2f64,
0x2da83000,0xada8b000,0x2da83000,0xada8b000,0xada88000,0x2da88000,0xada88000,0x2da80000,0x2da88000,0xada88000,0x2da80000,0xada80000,0x2da83000,0xada8b000,0x2da83000,0xada8b000,
0xa63eac72,0x2fd92ea7,0x263e2c72,0xafd9aea7,0xaea7afd9,0x2c72263e,0x2ea72fd9,0xac72a63e,0xafd9aea7,0xa63eac72,0x2fd92ea7,0x263e2c72,0xac72a63e,0xaea7afd9,0x2c72263e,0x2ea72fd9,
0x2a1f2da8,0xaf64ada8,0xaa1fada8,0x2f642da8,0x2f643000,0xaa1f8000,0xaf64b000,0x2a1f0000,0x2f642da8,0x2a1f2da8,0xaf64ada8,0xaa1fada8,0x2a1f8000,0x2f643000,0xaa1f8000,0xaf64b000,
0x3c003c00,0x3c003c00,0x3c003c00,0x3c003c00,0x3c003c00,0x3c003c00,0x3c003c00,0x3c003c00,0x80008000,0x80008000,0x80008000,0x80008000,0x80008000,0x80008000,0x80008000,0x80008000,
0x3bd93c00,0x3aa73b64,0x387239a8,0x323e361f,0xb23e0000,0xb872b61f,0xbaa7b9a8,0xbbd9bb64,0xb23e8000,0xb872b61f,0xbaa7b9a8,0xbbd9bb64,0xbbd9bc00,0xbaa7bb64,0xb872b9a8,0xb23eb61f,
0xbb64bc00,0xb61fb9a8,0x361f8000,0x3b6439a8,0x3b643c00,0x361f39a8,0xb61f0000,0xbb64b9a8,0x361f8000,0x3b6439a8,0x3b643c00,0x361f39a8,0xb61f8000,0xbb64b9a8,0xbb64bc00,0xb61fb9a8,
0x38728000,0x3bd93b64,0x323e39a8,0xbaa7b61f,0x3aa73c00,0xb23e361f,0xbbd9b9a8,0xb872bb64,0x3aa73c00,0xb23e361f,0xbbd9b9a8,0xb872bb64,0xb8728000,0xbbd9bb64,0xb23eb9a8,0x3aa7361f,
0xbc008000,0x3c008000,0xbc000000,0x3c008000,0xbc000000,0x3c008000,0xbc000000,0x3c008000,0x3c00,0x8000bc00,0x3c00,0x8000bc00,0x3c00,0x8000bc00,0x80003c00,0x8000bc00,
0xbbd98000,0x3aa7361f,0xb872b9a8,0x323e3b64,0x323ebc00,0xb8723b64,0x3aa7b9a8,0xbbd9361f,0xb23e3c00,0x3872bb64,0xbaa739a8,0x3bd9b61f,0xbbd90000,0x3aa7361f,0xb872b9a8,0x323e3b64,
0x3b648000,0xb61fb9a8,0xb61f3c00,0x3b64b9a8,0xbb648000,0x361f39a8,0x361fbc00,0xbb6439a8,0x361fbc00,0xbb6439a8,0x3b648000,0xb61fb9a8,0xb61f3c00,0x3b64b9a8,0xbb640000,0x361f39a8,
0xb8723c00,0x3bd9b61f,0xb23eb9a8,0xbaa73b64,0xbaa78000,0xb23e3b64,0x3bd9b9a8,0xb872b61f,0x3aa78000,0x323ebb64,0xbbd939a8,0x3872361f,0xb8723c00,0x3bd9b61f,0xb23eb9a8,0xbaa73b64,
0xbbd93c00,0xbaa73b64,0xb87239a8,0xb23e361f,0x323e8000,0x3872b61f,0x3aa7b9a8,0x3bd9bb64,0x323e8000,0x3872b61f,0x3aa7b9a8,0x3bd9bb64,0x3bd9bc00,0x3aa7bb64,0x3872b9a8,0x323eb61f,
0xbc003c00,0xbc003c00,0xbc003c00,0xbc003c00,0xbc003c00,0xbc003c00,0xbc003c00,0xbc003c00,0x80008000,0x80000000,0x80000000,0x80000000,0x80000000,0x80000000,0x0,0x80000000,
0xb8728000,0xbbd93b64,0xb23e39a8,0x3aa7b61f,0xbaa73c00,0x323e361f,0x3bd9b9a8,0x3872bb64,0xbaa73c00,0x323e361f,0x3bd9b9a8,0x3872bb64,0x38728000,0x3bd9bb64,0x323eb9a8,0xbaa7361f,
0x3b64bc00,0x361fb9a8,0xb61f8000,0xbb6439a8,0xbb643c00,0xb61f39a8,0x361f0000,0x3b64b9a8,0xb61f8000,0xbb6439a8,0xbb643c00,0xb61f39a8,0x361f8000,0x3b64b9a8,0x3b64bc00,0x361fb9a8,
0x3bd98000,0xbaa7361f,0x3872b9a8,0xb23e3b64,0xb23ebc00,0x38723b64,0xbaa7b9a8,0x3bd9361f,0x323e3c00,0xb872bb64,0x3aa739a8,0xbbd9b61f,0x3bd98000,0xbaa7361f,0x3872b9a8,0xb23e3b64,
0x3c008000,0xbc008000,0x3c000000,0xbc008000,0x3c000000,0xbc008000,0x3c000000,0xbc000000,0x80003c00,0xbc00,0x80003c00,0x8000bc00,0x80003c00,0xbc00,0x80003c00,0xbc00,
0x38723c00,0xbbd9b61f,0x323eb9a8,0x3aa73b64,0x3aa78000,0x323e3b64,0xbbd9b9a8,0x3872b61f,0xbaa78000,0xb23ebb64,0x3bd939a8,0xb872361f,0x38723c00,0xbbd9b61f,0x323eb9a8,0x3aa73b64,
0xbb640000,0x361fb9a8,0x361f3c00,0xbb64b9a8,0x3b648000,0xb61f39a8,0xb61fbc00,0x3b6439a8,0xb61fbc00,0x3b6439a8,0xbb640000,0x361fb9a8,0x361f3c00,0xbb64b9a8,0x3b648000,0xb61f39a8,
0x39a83c00,0xb9a80000,0xb9a8bc00,0x39a88000,0x39a83c00,0xb9a80000,0xb9a8bc00,0x39a88000,0xb9a88000,0xb9a8bc00,0x39a88000,0x39a83c00,0xb9a80000,0xb9a8bc00,0x39a88000,0x39a83c00,
0x38723c00,0xbbd9b61f,0x323eb9a8,0x3aa73b64,0xbaa70000,0xb23ebb64,0x3bd939a8,0xb872361f,0xbaa78000,0xb23ebb64,0x3bd939a8,0xb872361f,0xb872bc00,0x3bd9361f,0xb23e39a8,0xbaa7bb64,
0xb61fbc00,0x3b6439a8,0xbb640000,0x361fb9a8,0x361f3c00,0xbb64b9a8,0x3b648000,0xb61f39a8,0x3b648000,0xb61f39a8,0xb61fbc00,0x3b6439a8,0xbb648000,0x361fb9a8,0x361f3c00,0xbb64b9a8,
0x3bd98000,0xbaa7361f,0x3872b9a8,0xb23e3b64,0x323e3c00,0xb872bb64,0x3aa739a8,0xbbd9b61f,0x323e3c00,0xb872bb64,0x3aa739a8,0xbbd9b61f,0xbbd98000,0x3aa7b61f,0xb87239a8,0x323ebb64,
0xb9a88000,0xb9a83c00,0x39a88000,0x39a8bc00,0xb9a80000,0xb9a83c00,0x39a88000,0x39a8bc00,0xb9a83c00,0x39a88000,0x39a8bc00,0xb9a80000,0xb9a83c00,0x39a88000,0x39a8bc00,0xb9a88000,
0xb8728000,0xbbd93b64,0xb23e39a8,0x3aa7b61f,0x3aa7bc00,0xb23eb61f,0xbbd939a8,0xb8723b64,0xbaa73c00,0x323e361f,0x3bd9b9a8,0x3872bb64,0xb8728000,0xbbd93b64,0xb23e39a8,0x3aa7b61f,
0x361f8000,0x3b64b9a8,0x3b64bc00,0x361fb9a8,0xb61f8000,0xbb6439a8,0xbb643c00,0xb61f39a8,0x3b64bc00,0x361fb9a8,0xb61f8000,0xbb6439a8,0xbb643c00,0xb61f39a8,0x361f8000,0x3b64b9a8,
0xbbd93c00,0xbaa73b64,0xb87239a8,0xb23e361f,0xb23e8000,0xb872361f,0xbaa739a8,0xbbd93b64,0x323e8000,0x3872b61f,0x3aa7b9a8,0x3bd9bb64,0xbbd93c00,0xbaa73b64,0xb87239a8,0xb23e361f,
0xb8723c00,0x3bd9b61f,0xb23eb9a8,0xbaa73b64,0x3aa78000,0x323ebb64,0xbbd939a8,0x3872361f,0x3aa78000,0x323ebb64,0xbbd939a8,0x3872361f,0x3872bc00,0xbbd9361f,0x323e39a8,0x3aa7bb64,
0xb9a83c00,0x39a80000,0x39a8bc00,0xb9a88000,0xb9a83c00,0x39a88000,0x39a8bc00,0xb9a88000,0x39a88000,0x39a8bc00,0xb9a88000,0xb9a83c00,0x39a80000,0x39a8bc00,0xb9a88000,0xb9a83c00,
0xbbd98000,0x3aa7361f,0xb872b9a8,0x323e3b64,0xb23e3c00,0x3872bb64,0xbaa739a8,0x3bd9b61f,0xb23e3c00,0x3872bb64,0xbaa739a8,0x3bd9b61f,0x3bd98000,0xbaa7b61f,0x387239a8,0xb23ebb64,
0x361fbc00,0xbb6439a8,0x3b640000,0xb61fb9a8,0xb61f3c00,0x3b64b9a8,0xbb648000,0x361f39a8,0xbb648000,0x361f39a8,0x361fbc00,0xbb6439a8,0x3b648000,0xb61fb9a8,0xb61f3c00,0x3b64b9a8,
0x38728000,0x3bd93b64,0x323e39a8,0xbaa7b61f,0xbaa7bc00,0x323eb61f,0x3bd939a8,0x38723b64,0x3aa73c00,0xb23e361f,0xbbd9b9a8,0xb872bb64,0x38728000,0x3bd93b64,0x323e39a8,0xbaa7b61f,
0x39a88000,0x39a83c00,0xb9a88000,0xb9a8bc00,0x39a80000,0x39a83c00,0xb9a80000,0xb9a8bc00,0x39a83c00,0xb9a88000,0xb9a8bc00,0x39a88000,0x39a83c00,0xb9a88000,0xb9a8bc00,0x39a80000,
0x3bd93c00,0x3aa73b64,0x387239a8,0x323e361f,0x323e8000,0x3872361f,0x3aa739a8,0x3bd93b64,0xb23e8000,0xb872b61f,0xbaa7b9a8,0xbbd9bb64,0x3bd93c00,0x3aa73b64,0x387239a8,0x323e361f,
0xb61f8000,0xbb64b9a8,0xbb64bc00,0xb61fb9a8,0x361f8000,0x3b6439a8,0x3b643c00,0x361f39a8,0xbb64bc00,0xb61fb9a8,0x361f0000,0x3b6439a8,0x3b643c00,0x361f39a8,0xb61f8000,0xbb64b9a8,
0x0,0x0,0x0,0x0,0x0,0x0,0x0,0x0,0x3c003c00,0x3c003c00,0x3c003c00,0x3c003c00,0x3c003c00,0x3c003c00,0x3c003c00,0x3c003c00,
0x323e0000,0x3872361f,0x3aa739a8,0x3bd93b64,0x3bd93c00,0x3aa73b64,0x387239a8,0x323e361f,0x3bd93c00,0x3aa73b64,0x387239a8,0x323e361f,0xb23e0000,0xb872b61f,0xbaa7b9a8,0xbbd9bb64,
0xb61f0000,0xbb64b9a8,0xbb64bc00,0xb61fb9a8,0x361f0000,0x3b6439a8,0x3b643c00,0x361f39a8,0xbb64bc00,0xb61fb9a8,0x361f8000,0x3b6439a8,0x3b643c00,0x361f39a8,0xb61f0000,0xbb64b9a8,
0xbaa7bc00,0x323eb61f,0x3bd939a8,0x38723b64,0x38720000,0x3bd93b64,0x323e39a8,0xbaa7b61f,0x38728000,0x3bd93b64,0x323e39a8,0xbaa7b61f,0x3aa73c00,0xb23e361f,0xbbd9b9a8,0xb872bb64,
0x3c00,0x8000bc00,0x3c00,0x8000bc00,0x3c00,0x8000bc00,0x80003c00,0x8000bc00,0x3c000000,0xbc000000,0x3c008000,0xbc000000,0x3c008000,0xbc000000,0x3c008000,0xbc000000,
0xb23e3c00,0x3872bb64,0xbaa739a8,0x3bd9b61f,0xbbd90000,0x3aa7361f,0xb872b9a8,0x323e3b64,0x3bd90000,0xbaa7b61f,0x387239a8,0xb23ebb64,0xb23e3c00,0x3872bb64,0xbaa739a8,0x3bd9b61f,
0x361fbc00,0xbb6439a8,0x3b648000,0xb61fb9a8,0xb61f3c00,0x3b64b9a8,0xbb640000,0x361f39a8,0xbb640000,0x361f39a8,0x361fbc00,0xbb6439a8,0x3b640000,0xb61fb9a8,0xb61f3c00,0x3b64b9a8,
0x3aa78000,0x323ebb64,0xbbd939a8,0x3872361f,0xb8723c00,0x3bd9b61f,0xb23eb9a8,0xbaa73b64,0x3872bc00,0xbbd9361f,0x323e39a8,0x3aa7bb64,0x3aa70000,0x323ebb64,0xbbd939a8,0x3872361f,
0xb23e0000,0xb872361f,0xbaa739a8,0xbbd93b64,0xbbd93c00,0xbaa73b64,0xb87239a8,0xb23e361f,0xbbd93c00,0xbaa73b64,0xb87239a8,0xb23e361f,0x323e8000,0x3872b61f,0x3aa7b9a8,0x3bd9bb64,
0x0,0x8000,0x8000,0x8000,0x8000,0x8000,0x80008000,0x8000,0xbc003c00,0xbc003c00,0xbc003c00,0xbc003c00,0xbc003c00,0xbc003c00,0xbc003c00,0xbc003c00,
0x3aa7bc00,0xb23eb61f,0xbbd939a8,0xb8723b64,0xb8720000,0xbbd93b64,0xb23e39a8,0x3aa7b61f,0xb8728000,0xbbd93b64,0xb23e39a8,0x3aa7b61f,0xbaa73c00,0x323e361f,0x3bd9b9a8,0x3872bb64,
0x361f0000,0x3b64b9a8,0x3b64bc00,0x361fb9a8,0xb61f0000,0xbb6439a8,0xbb643c00,0xb61f39a8,0x3b64bc00,0x361fb9a8,0xb61f8000,0xbb6439a8,0xbb643c00,0xb61f39a8,0x361f0000,0x3b64b9a8,
0x323e3c00,0xb872bb64,0x3aa739a8,0xbbd9b61f,0x3bd98000,0xbaa7361f,0x3872b9a8,0xb23e3b64,0xbbd90000,0x3aa7b61f,0xb87239a8,0x323ebb64,0x323e3c00,0xb872bb64,0x3aa739a8,0xbbd9b61f,
0x80003c00,0xbc00,0x80003c00,0x8000bc00,0x80003c00,0xbc00,0x80003c00,0xbc00,0xbc000000,0x3c000000,0xbc008000,0x3c000000,0xbc008000,0x3c000000,0xbc008000,0x3c008000,
0xbaa78000,0xb23ebb64,0x3bd939a8,0xb872361f,0x38723c00,0xbbd9b61f,0x323eb9a8,0x3aa73b64,0xb872bc00,0x3bd9361f,0xb23e39a8,0xbaa7bb64,0xbaa70000,0xb23ebb64,0x3bd939a8,0xb872361f,
0xb61fbc00,0x3b6439a8,0xbb640000,0x361fb9a8,0x361f3c00,0xbb64b9a8,0x3b648000,0xb61f39a8,0x3b648000,0xb61f39a8,0xb61fbc00,0x3b6439a8,0xbb640000,0x361fb9a8,0x361f3c00,0xbb64b9a8,
0x39a80000,0x39a83c00,0xb9a80000,0xb9a8bc00,0x39a88000,0x39a83c00,0xb9a80000,0xb9a8bc00,0x39a83c00,0xb9a80000,0xb9a8bc00,0x39a88000,0x39a83c00,0xb9a80000,0xb9a8bc00,0x39a88000,
0x3aa70000,0x323e3b64,0xbbd9b9a8,0x3872b61f,0x38723c00,0xbbd9b61f,0x323eb9a8,0x3aa73b64,0x38723c00,0xbbd9b61f,0x323eb9a8,0x3aa73b64,0xbaa70000,0xb23ebb64,0x3bd939a8,0xb872361f,
0xbb640000,0x361fb9a8,0x361f3c00,0xbb64b9a8,0x3b640000,0xb61f39a8,0xb61fbc00,0x3b6439a8,0xb61fbc00,0x3b6439a8,0xbb640000,0x361fb9a8,0x361f3c00,0xbb64b9a8,0x3b648000,0xb61f39a8,
0xb23ebc00,0x38723b64,0xbaa7b9a8,0x3bd9361f,0x3bd90000,0xbaa7361f,0x3872b9a8,0xb23e3b64,0x3bd98000,0xbaa7361f,0x3872b9a8,0xb23e3b64,0x323e3c00,0xb872bb64,0x3aa739a8,0xbbd9b61f,
0xb9a83c00,0x39a88000,0x39a8bc00,0xb9a80000,0xb9a83c00,0x39a88000,0x39a8bc00,0xb9a88000,0x39a80000,0x39a8bc00,0xb9a80000,0xb9a83c00,0x39a88000,0x39a8bc00,0xb9a80000,0xb9a83c00,
0xbaa73c00,0x323e361f,0x3bd9b9a8,0x3872bb64,0xb8728000,0xbbd93b64,0xb23e39a8,0x3aa7b61f,0x38720000,0x3bd9bb64,0x323eb9a8,0xbaa7361f,0xbaa73c00,0x323e361f,0x3bd9b9a8,0x3872bb64,
0x3b64bc00,0x361fb9a8,0xb61f8000,0xbb6439a8,0xbb643c00,0xb61f39a8,0x361f8000,0x3b64b9a8,0xb61f0000,0xbb6439a8,0xbb643c00,0xb61f39a8,0x361f0000,0x3b64b9a8,0x3b64bc00,0x361fb9a8,
0x323e8000,0x3872b61f,0x3aa7b9a8,0x3bd9bb64,0xbbd93c00,0xbaa73b64,0xb87239a8,0xb23e361f,0x3bd9bc00,0x3aa7bb64,0x3872b9a8,0x323eb61f,0x323e0000,0x3872b61f,0x3aa7b9a8,0x3bd9bb64,
0xbaa70000,0xb23e3b64,0x3bd9b9a8,0xb872b61f,0xb8723c00,0x3bd9b61f,0xb23eb9a8,0xbaa73b64,0xb8723c00,0x3bd9b61f,0xb23eb9a8,0xbaa73b64,0x3aa78000,0x323ebb64,0xbbd939a8,0x3872361f,
0xb9a80000,0xb9a83c00,0x39a80000,0x39a8bc00,0xb9a88000,0xb9a83c00,0x39a80000,0x39a8bc00,0xb9a83c00,0x39a80000,0x39a8bc00,0xb9a88000,0xb9a83c00,0x39a88000,0x39a8bc00,0xb9a88000,
0x323ebc00,0xb8723b64,0x3aa7b9a8,0xbbd9361f,0xbbd90000,0x3aa7361f,0xb872b9a8,0x323e3b64,0xbbd98000,0x3aa7361f,0xb872b9a8,0x323e3b64,0xb23e3c00,0x3872bb64,0xbaa739a8,0x3bd9b61f,
0x3b640000,0xb61fb9a8,0xb61f3c00,0x3b64b9a8,0xbb640000,0x361f39a8,0x361fbc00,0xbb6439a8,0x361fbc00,0xbb6439a8,0x3b640000,0xb61fb9a8,0xb61f3c00,0x3b64b9a8,0xbb648000,0x361f39a8,
0x3aa73c00,0xb23e361f,0xbbd9b9a8,0xb872bb64,0x38728000,0x3bd93b64,0x323e39a8,0xbaa7b61f,0xb8720000,0xbbd9bb64,0xb23eb9a8,0x3aa7361f,0x3aa73c00,0xb23e361f,0xbbd9b9a8,0xb872bb64,
0x39a83c00,0xb9a88000,0xb9a8bc00,0x39a88000,0x39a83c00,0xb9a88000,0xb9a8bc00,0x39a80000,0xb9a80000,0xb9a8bc00,0x39a80000,0x39a83c00,0xb9a88000,0xb9a8bc00,0x39a88000,0x39a83c00,
0xb23e8000,0xb872b61f,0xbaa7b9a8,0xbbd9bb64,0x3bd93c00,0x3aa73b64,0x387239a8,0x323e361f,0xbbd9bc00,0xbaa7bb64,0xb872b9a8,0xb23eb61f,0xb23e0000,0xb872b61f,0xbaa7b9a8,0xbbd9bb64,
0xbb64bc00,0xb61fb9a8,0x361f0000,0x3b6439a8,0x3b643c00,0x361f39a8,0xb61f8000,0xbb64b9a8,0x361f0000,0x3b6439a8,0x3b643c00,0x361f39a8,0xb61f0000,0xbb64b9a8,0xbb64bc00,0xb61fb9a8,
};
__device__ __align__(1024) bf16 g_x1T[DM * XP];
__device__ __align__(1024) bf16 g_x2T[DM * XP];
__device__ __align__(1024) unsigned g_xcnt[10][4][32];
__device__ __align__(1024) uint4 g_of[8][16][1280];
__device__ __align__(1024) float g_fs[2][SEQ];

#define TS_SMEM 0
#define TS_DECL
#define TS_ARG
#define TS_PASS
#define TS_PHASE(p)
#define TS(i)
#define TSX(row, i)
#define TS_BEGIN
#define TS_END

struct cplx { float r, i; };
__device__ __forceinline__ cplx cmul(cplx a, cplx b) {
    cplx o;
    o.r = fmaf(a.r, b.r, -a.i * b.i);
    o.i = fmaf(a.r, b.i, a.i * b.r);
    return o;
}
__device__ __forceinline__ cplx csq(cplx a) {
    cplx o;
    o.r = fmaf(a.r, a.r, -a.i * a.i);
    o.i = 2.f * a.r * a.i;
    return o;
}
__device__ __forceinline__ cplx cexp_p(float arl, float ai, float p) {
    float mag = ex2(arl * p);
    float ang = ai * p;
    float n = rintf(ang * 0.15915494309189535f);
    float r = fmaf(n, -6.2831854820251465f, ang);
    r = fmaf(n, 1.7484555e-7f, r);
    cplx o;
    o.r = mag * __cosf(r);
    o.i = mag * __sinf(r);
    return o;
}

__device__ __forceinline__ uint32_t pack2h(float lo, float hi) {
    uint32_t r;
    asm("cvt.rn.f16x2.f32 %0, %1, %2;" : "=r"(r) : "f"(hi), "f"(lo));
    return r;
}
__device__ __forceinline__ uint32_t hmul(uint32_t a, uint32_t b) { uint32_t d; asm("mul.rn.f16x2 %0, %1, %2;" : "=r"(d) : "r"(a), "r"(b)); return d; }
__device__ __forceinline__ uint32_t hfma(uint32_t a, uint32_t b, uint32_t c) { uint32_t d; asm("fma.rn.f16x2 %0, %1, %2, %3;" : "=r"(d) : "r"(a), "r"(b), "r"(c)); return d; }
__device__ __forceinline__ uint32_t hfms(uint32_t a, uint32_t b, uint32_t c) {
    uint32_t d;
    asm("{\n.reg .b32 n;\nneg.f16x2 n, %1;\nfma.rn.f16x2 %0, n, %2, %3;\n}" : "=r"(d) : "r"(a), "r"(b), "r"(c));
    return d;
}
__device__ __forceinline__ uint32_t hadd(uint32_t a, uint32_t b) { uint32_t d; asm("add.rn.f16x2 %0, %1, %2;" : "=r"(d) : "r"(a), "r"(b)); return d; }
__device__ __forceinline__ uint32_t hsub(uint32_t a, uint32_t b) { uint32_t d; asm("sub.rn.f16x2 %0, %1, %2;" : "=r"(d) : "r"(a), "r"(b)); return d; }
__device__ __forceinline__ uint4 ldg_tab(int tab, int t) { return ldg128((const uint4*)c_fft + t + tab * 128); }
__device__ __forceinline__ uint32_t u4(const uint4& v, int i) { return i == 0 ? v.x : i == 1 ? v.y : i == 2 ? v.z : v.w; }
struct cpair { uint32_t r, i; };
__device__ __forceinline__ cpair pmul(cpair p, uint32_t z) {
    const __half2 zv = *reinterpret_cast<const __half2*>(&z), pr = *reinterpret_cast<const __half2*>(&p.r), pi = *reinterpret_cast<const __half2*>(&p.i);
    const __half2 zr = __low2half2(zv), zi = __high2half2(zv);
    const __half2 a = __hfma2(__hneg2(pi), zi, __hmul2(pr, zr)), b = __hfma2(pi, zr, __hmul2(pr, zi));
    return {*reinterpret_cast<const uint32_t*>(&a), *reinterpret_cast<const uint32_t*>(&b)};
}
__device__ __forceinline__ uint32_t packz(cplx z) { return pack2h(z.r, z.i); }
__device__ __forceinline__ void wgmma_kg(float (&d)[24], uint64_t da, uint64_t db, int scale_d) {
    asm volatile("{\n.reg .pred p;\nsetp.ne.b32 p, %26, 0;\n"
                 "wgmma.mma_async.sync.aligned.m64n48k16.f32.f16.f16 "
                 "{%0,%1,%2,%3,%4,%5,%6,%7,%8,%9,%10,%11,%12,%13,%14,%15,%16,%17,%18,%19,%20,%21,%22,%23}, %24, %25, p, 1, 1, 1, 1;\n}\n"
                 : "+f"(d[0]), "+f"(d[1]), "+f"(d[2]), "+f"(d[3]), "+f"(d[4]), "+f"(d[5]), "+f"(d[6]), "+f"(d[7]), "+f"(d[8]), "+f"(d[9]),
                   "+f"(d[10]), "+f"(d[11]), "+f"(d[12]), "+f"(d[13]), "+f"(d[14]), "+f"(d[15]), "+f"(d[16]), "+f"(d[17]), "+f"(d[18]), "+f"(d[19]),
                   "+f"(d[20]), "+f"(d[21]), "+f"(d[22]), "+f"(d[23])
                 : "l"(da), "l"(db), "r"(scale_d));
}

struct SsmParams { const bf16 *lar, *aim, *cre, *cim, *logdt, *dskip; const unsigned* epoch; };
constexpr int KG_TABLES = 6 * 16384, KG_RES = 1664;
struct KgShared { uint32_t kmax[6], kexp[6]; float cinv[6], tap0[6]; };
#define KS(f, i) (ks + (uint32_t)offsetof(KgShared, f) + 4 * (i))
struct KgParams { uint32_t l[3], a[3], r[3], i[3], dt, ds; };

__device__ __forceinline__ int cta_channel(int bx, int i) { return i < 2 ? 2 * bx + i : i < 4 ? 382 + 2 * bx + i : 256 + bx; }
__device__ __forceinline__ bool kg_is_hi(int warp) { return ((warp >> 1) ^ (warp >> 2)) & 1; }
__device__ __forceinline__ void kgen_load(KgParams& kp, int bx, int warp, int lane, const SsmParams& sp) {
    const int d = cta_channel(bx, 2 * (warp >> 2) + (warp & 1)), idx = d * (NMODE / 2) + lane;
    const bf16 *pr = kg_is_hi(warp) ? sp.cre : sp.lar, *pi = kg_is_hi(warp) ? sp.cim : sp.aim;
    kp.dt = __ldg((const uint16_t*)sp.logdt + d);
#pragma unroll
    for (int j = 0; j < 3; j++) {
        kp.l[j] = __ldg((const uint32_t*)sp.lar + idx + 32 * j); kp.a[j] = __ldg((const uint32_t*)sp.aim + idx + 32 * j);
        kp.r[j] = __ldg((const uint32_t*)pr + idx + 32 * j); kp.i[j] = __ldg((const uint32_t*)pi + idx + 32 * j);
    }
    kp.ds = __ldg((const uint16_t*)sp.dskip + cta_channel(bx, warp >> 1));
}

struct KgAnchors { uint32_t v[8]; };
__device__ __forceinline__ KgAnchors kg_anchor_lo(const KgParams& kp, uint32_t sel, float dt) {
    auto B = [&](uint32_t v) { return __uint_as_float(__byte_perm(v, 0u, sel)); };
    const float arl = -rbf(ex2(B(kp.l[0]) * 1.4426950408889634f)) * dt * 1.4426950408889634f, ai = B(kp.a[0]) * dt;
    const cplx z8 = cexp_p(arl, ai, 8.f), z16 = csq(z8), z24 = cmul(z16, z8), z32 = csq(z16), z64 = csq(z32), z128 = csq(z64), z192 = cmul(z128, z64);
    return {{pack2h(1.f, z8.r), pack2h(0.f, z8.i), pack2h(z16.r, z24.r), pack2h(z16.i, z24.i), packz(z32), packz(z64), packz(z128), packz(z192)}};
}
__device__ __forceinline__ KgAnchors kg_anchor_hi(const KgParams& kp, uint32_t sel, float dt, float cs) {
    auto B = [&](uint32_t v) { return __uint_as_float(__byte_perm(v, 0u, sel)); };
    const float arl = -rbf(ex2(B(kp.l[0]) * 1.4426950408889634f)) * dt * 1.4426950408889634f, ai = B(kp.a[0]) * dt;
    const cplx z1 = cexp_p(arl, -ai, 1.f), z2 = csq(z1), z4 = csq(z2), z256 = cexp_p(arl, -ai, 256.f), z512 = csq(z256), z1024 = csq(z512);
    const cplx H0 = {B(kp.r[0]) * cs, -B(kp.i[0]) * cs}, H4 = cmul(H0, z4);
    return {{pack2h(H0.r, H4.r), pack2h(H0.i, H4.i), packz(z1), packz(z2), packz(z256), packz(z512), packz(z1024), 0u}};
}

template <class Idle>
__device__ __forceinline__ void kgen_tables(KgParams& kp, uint32_t scr, uint32_t dump, uint32_t ks, int warp, int lane, Idle idle TS_ARG) {
    const int wg = warp >> 2, half = warp & 1, sw = lane & 7;
    const bool hi = kg_is_hi(warp);
    TS(23);
    const float dt = rbf(ex2(bf_lo(kp.dt) * 1.4426950408889634f));
    uint32_t sel = (wg == 2 && half) ? 0x3244u : 0x1044u;
    float cs = 0.f;
    KgAnchors an;
    if (hi) {
        uint32_t m = 0;
#pragma unroll
        for (int j = 0; j < 3; j++) m = __vmaxu2(m, __vmaxu2(kp.r[j] & 0x7FFF7FFFu, kp.i[j] & 0x7FFF7FFFu));
        m = __reduce_max_sync(~0u, max(m << 16, m & 0xFFFF0000u));
        const uint32_t e = min(max(__float_as_uint(2.f * dt * __uint_as_float(m)) >> 23, 2u), 252u);
        cs = 2.f * dt * __uint_as_float((253u - e) << 23);
        if (lane == 0) { sts32(KS(cinv, 2 * wg + half), (e + 1u) << 23); sts32(KS(kmax, 2 * wg + half), 0u); }
        an = kg_anchor_hi(kp, sel, dt, cs);
    } else {
        an = kg_anchor_lo(kp, sel, dt);
    }
    float acc[24];
#pragma unroll
    for (int i = 0; i < 24; i++) acc[i] = 0.f;
    uint32_t tb = scr + 2 * wg * 16384 + lane * 128;
    uint64_t da = mkdesc(scr + 2 * wg * 16384, 4096, 1024, 1);
    int flip = 16384;
#pragma unroll 1
    for (int c = wg == 2 ? 1 : 0, step = wg == 2 ? 2 : 1; c < 6; c += step) {
        if (wg < 2) sel ^= 0x2200u;
        if (!hi) {
            if (c & 1) { kp.l[0] = kp.l[1]; kp.l[1] = kp.l[2]; kp.a[0] = kp.a[1]; kp.a[1] = kp.a[2]; }
            cpair p[4];
            p[0] = {an.v[0], an.v[1]}; p[1] = {an.v[2], an.v[3]};
            p[2] = pmul(p[0], an.v[4]); p[3] = pmul(p[1], an.v[4]);
#pragma unroll
            for (int j = 0; j < 4; j++) {
                cpair v[4];
#pragma unroll
                for (int i = 0; i < 4; i++) v[i] = j ? pmul(p[i], an.v[4 + j]) : p[i];
                const uint32_t a = tb + (((4 * half + j) ^ sw) << 4);
                sts128(a, make_uint4(v[0].r, v[1].r, v[2].r, v[3].r));
                sts128(a + 4096, make_uint4(v[0].i, v[1].i, v[2].i, v[3].i));
            }
            an = kg_anchor_lo(kp, sel, dt);
        } else {
            if (c & 1) {
#pragma unroll
                for (int j = 0; j < 2; j++) { kp.l[j] = kp.l[j + 1]; kp.a[j] = kp.a[j + 1]; kp.r[j] = kp.r[j + 1]; kp.i[j] = kp.i[j + 1]; }
            }
            const uint32_t h1 = an.v[2], h2 = an.v[3], h256 = an.v[4], h512 = an.v[5], h1024 = an.v[6];
            cpair p[11];
            p[0] = {an.v[0], an.v[1]};
            p[1] = pmul(p[0], h2); p[2] = pmul(p[0], h1); p[3] = pmul(p[1], h1);
            p[4] = pmul(p[0], h256); p[5] = pmul(p[1], h256); p[6] = pmul(p[0], h512); p[7] = pmul(p[4], h512);
            p[8] = pmul({__byte_perm(p[0].r, p[4].r, 0x5410), __byte_perm(p[0].i, p[4].i, 0x5410)}, h1024);
            p[9] = pmul(p[8], h512); p[10] = pmul(p[8], h1024);
#pragma unroll
            for (int j = 0; j < 3; j++) {
                const uint32_t a = tb + 8192 + (((3 * half + j) ^ sw) << 4);
                sts128(a, make_uint4(p[4 * j].r, p[4 * j + 1].r, p[4 * j + 2].r, p[j < 2 ? 4 * j + 3 : 10].r));
                sts128(a + 4096, make_uint4(p[4 * j].i, p[4 * j + 1].i, p[4 * j + 2].i, p[j < 2 ? 4 * j + 3 : 10].i));
            }
            an = kg_anchor_hi(kp, sel, dt, cs);
        }
        if (c == 0) TS(24);
        if (c == 3) TS(25);
        fence_async_smem();
        wg_wait<0>();
        named_bar(5 + wg, 128);
        wg_fence();
#pragma unroll
        for (int k = 0; k < 4; k++) wgmma_kg(acc, da + k * 128, da + 512 + k * 128, 1);
        wg_commit();
        tb += flip; da += flip >> 4; flip = -flip;
    }
    const bool up = warp & 2;
    const int r = 2 * wg + up, lo0 = 16 * half + (lane >> 2);
    const uint32_t o = dump + r * KG_RES + lo0 * 52 + 4 * (lane & 3);
    const float ci = __uint_as_float(lds32(KS(cinv, r)));
    const float ds = warp <= 8 ? bf_lo(kp.ds) : 0.f;
    TS(26);
    idle();
    wg_wait<0>();
    float v[12], m = 0.f;
#pragma unroll
    for (int j = 0; j < 12; j++) { v[j] = up ? acc[12 + j] : acc[j]; m = fmaxf(m, fabsf(v[j])); }
#pragma unroll
    for (int j = 0; j < 6; j++) sts32(o + (j & 1) * 416 + (j >> 1) * 16, pack2h(v[2 * j], v[2 * j + 1]));
    const uint32_t mm = __reduce_max_sync(~0u, __float_as_uint(m));
    if (lane == 0) {
        asm volatile("red.shared.max.u32 [%0], %1;" ::"r"(KS(kmax, r)), "r"(mm) : "memory");
        if (!half) sts32(KS(tap0, r), __float_as_uint(fmaf(ci, v[0], ds)));
    }
}
#define F_STAG 4
__device__ __forceinline__ void wgmma_h64_rs(uint32_t (&d)[16], const uint4& a, uint64_t db, int scale_d) {
    asm volatile("{\n.reg .pred p;\nsetp.ne.b32 p, %21, 0;\n"
                 "wgmma.mma_async.sync.aligned.m64n64k16.f16.f16.f16 {%0,%1,%2,%3,%4,%5,%6,%7,%8,%9,%10,%11,%12,%13,%14,%15}, {%16,%17,%18,%19}, %20, p, 1, 1, 1;\n}\n"
                 : "+r"(d[0]), "+r"(d[1]), "+r"(d[2]), "+r"(d[3]), "+r"(d[4]), "+r"(d[5]), "+r"(d[6]), "+r"(d[7]), "+r"(d[8]), "+r"(d[9]),
                   "+r"(d[10]), "+r"(d[11]), "+r"(d[12]), "+r"(d[13]), "+r"(d[14]), "+r"(d[15])
                 : "r"(a.x), "r"(a.y), "r"(a.z), "r"(a.w), "l"(db), "r"(scale_d));
}
template <int TB>
__device__ __forceinline__ void wgmma_h32_rs(uint32_t (&d)[8], const uint4& a, uint64_t db, int scale_d) {
    asm volatile("{\n.reg .pred p;\nsetp.ne.b32 p, %13, 0;\n"
                 "wgmma.mma_async.sync.aligned.m64n32k16.f16.f16.f16 {%0,%1,%2,%3,%4,%5,%6,%7}, {%8,%9,%10,%11}, %12, p, 1, 1, %14;\n}\n"
                 : "+r"(d[0]), "+r"(d[1]), "+r"(d[2]), "+r"(d[3]), "+r"(d[4]), "+r"(d[5]), "+r"(d[6]), "+r"(d[7])
                 : "r"(a.x), "r"(a.y), "r"(a.z), "r"(a.w), "l"(db), "r"(scale_d), "n"(TB));
}
__device__ __forceinline__ void wgmma_s1(uint32_t (&d)[16], const uint4& a, uint64_t db, int scale_d) { wgmma_h64_rs(d, a, db, scale_d); }
__device__ __forceinline__ void wgmma_s1(uint32_t (&d)[8], const uint4& a, uint64_t db, int scale_d) { wgmma_h32_rs<1>(d, a, db, scale_d); }
__device__ __forceinline__ void wgmma_s4(float (&d)[32], const uint4& a, uint64_t db, uint32_t meta, int scale_d) {
    asm volatile("{\n.reg .pred p;\nsetp.ne.b32 p, %38, 0;\n"
                 "wgmma.mma_async.sp.sync.aligned.m64n64k32.f32.f16.f16 {%0,%1,%2,%3,%4,%5,%6,%7,%8,%9,%10,%11,%12,%13,%14,%15,%16,%17,%18,%19,%20,%21,%22,%23,%24,%25,%26,%27,%28,%29,%30,%31}, {%32,%33,%34,%35}, %36, %37, 0, p, 1, 1, 1;\n}\n"
                 : "+f"(d[0]), "+f"(d[1]), "+f"(d[2]), "+f"(d[3]), "+f"(d[4]), "+f"(d[5]), "+f"(d[6]), "+f"(d[7]), "+f"(d[8]), "+f"(d[9]), "+f"(d[10]), "+f"(d[11]), "+f"(d[12]), "+f"(d[13]), "+f"(d[14]), "+f"(d[15]), "+f"(d[16]), "+f"(d[17]), "+f"(d[18]), "+f"(d[19]), "+f"(d[20]), "+f"(d[21]), "+f"(d[22]), "+f"(d[23]), "+f"(d[24]), "+f"(d[25]), "+f"(d[26]), "+f"(d[27]), "+f"(d[28]), "+f"(d[29]), "+f"(d[30]), "+f"(d[31])
                 : "r"(a.x), "r"(a.y), "r"(a.z), "r"(a.w), "l"(db), "r"(meta), "r"(scale_d));
}
__device__ __forceinline__ void wgmma_s4(float (&d)[16], const uint4& a, uint64_t db, uint32_t meta, int scale_d) {
    asm volatile("{\n.reg .pred p;\nsetp.ne.b32 p, %22, 0;\n"
                 "wgmma.mma_async.sp.sync.aligned.m64n32k32.f32.f16.f16 {%0,%1,%2,%3,%4,%5,%6,%7,%8,%9,%10,%11,%12,%13,%14,%15}, {%16,%17,%18,%19}, %20, %21, 0, p, 1, 1, 1;\n}\n"
                 : "+f"(d[0]), "+f"(d[1]), "+f"(d[2]), "+f"(d[3]), "+f"(d[4]), "+f"(d[5]), "+f"(d[6]), "+f"(d[7]), "+f"(d[8]), "+f"(d[9]), "+f"(d[10]), "+f"(d[11]), "+f"(d[12]), "+f"(d[13]), "+f"(d[14]), "+f"(d[15])
                 : "r"(a.x), "r"(a.y), "r"(a.z), "r"(a.w), "l"(db), "r"(meta), "r"(scale_d));
}

__device__ __forceinline__ uint32_t& u4r(uint4& v, int i) { return i == 0 ? v.x : i == 1 ? v.y : i == 2 ? v.z : v.w; }

template <int NC>
__device__ __forceinline__ void fft_stage(const uint32_t (&u)[2][4], int c, uint32_t eo, int w, int lane) {
    const int mi = lane >> 3, mj = lane & 7;
    const uint32_t a = eo + (8 * w + mj) * 128 + (((4 * c + mi) ^ mj) << 4);
    stsm_x4(a, hadd(u[0][0], u[1][0]), hadd(u[0][1], u[1][1]), hadd(u[0][2], u[1][2]), hadd(u[0][3], u[1][3]));
    stsm_x4(NC == 2 ? a + 4096 : a ^ 64, hsub(u[0][0], u[1][0]), hsub(u[0][1], u[1][1]), hsub(u[0][2], u[1][2]), hsub(u[0][3], u[1][3]));
}
template <int NC>
__device__ __forceinline__ void kernel_stage(const uint4 (&ko)[2], uint32_t kt, uint32_t ks, int r, uint32_t eo, int w, int lane) {
    uint32_t u[2][2][4], sc[NC], t0[NC];
#pragma unroll
    for (int c = 0; c < NC; c++) {
        auto L = [](uint32_t a) { return __uint_as_float(lds32(a)); };
        const float ci = L(KS(cinv, r + c)), k0 = L(KS(tap0, r + c)) + (NC == 1 ? L(KS(tap0, r + 1)) : 0.f);
        const float mx = fmaxf(ci * (L(KS(kmax, r + c)) + (NC == 1 ? L(KS(kmax, r + 1)) : 0.f) + 0x1p-14f), fabsf(k0));
        const uint32_t e = min(max(__float_as_uint(mx) >> 23, 4u), 250u);
        const float s = __uint_as_float((253u - e) << 23), f = s * ci;
        if (w == 0 && lane == 0) sts32(KS(kexp, r + c), e);
        sc[c] = pack2h(f, f); t0[c] = pack2h(k0 * s, 0.f);
    }
#pragma unroll
    for (int h = 0; h < 2; h++)
#pragma unroll
        for (int j = 0; j < 4; j++) {
            const uint32_t a0 = kt + (u4(ko[h], j) & 0xFFFF), a1 = kt + (u4(ko[h], j) >> 16);
#pragma unroll
            for (int c = 0; c < 2; c++)
                asm volatile("{\n.reg .b16 a, b;\nld.shared.b16 a, [%1];\nld.shared.b16 b, [%2];\nmov.b32 %0, {a, b};\n}"
                             : "=r"(u[c][h][j]) : "r"(a0 + c * KG_RES), "r"(a1 + c * KG_RES) : "memory");
            if (NC == 1) u[0][h][j] = hadd(u[0][h][j], u[1][h][j]);
#pragma unroll
            for (int c = 0; c < NC; c++) {
                u[c][h][j] = hmul(u[c][h][j], sc[c]);
                if (h + j == 0 && w == 0 && lane == 0) u[c][0][0] = __byte_perm(t0[c], u[c][0][0], 0x7610);
            }
        }
#pragma unroll
    for (int c = 0; c < NC; c++) fft_stage<NC>(u[c], c, eo, w, lane);
}

template <int NC, bool SHEAR, class Mid>
__device__ __forceinline__ void fft_forward(const uint4 (&a1)[4], const uint4 (&tw)[4], uint32_t eo, uint32_t s2, uint32_t (&X)[NC][2][8], Mid mid) {
    uint32_t dr[8 * NC], di[8 * NC];
    const uint64_t de = mkdesc(eo, 4096, 1024, 1), d2 = mkdesc(s2, 16, 1024, 1);
    wg_fence();
    wgmma_s1(dr, a1[0], de, 0);
    wgmma_s1(di, a1[2], de + (NC == 2 ? 256 : 4), 0);
    wgmma_s1(dr, a1[1], de + 128, 1);
    wgmma_s1(di, a1[3], de + (NC == 2 ? 384 : 132), 1);
    wg_commit();
    mid();
    wg_wait<0>();
#pragma unroll
    for (int c = 0; c < NC; c++) {
        uint4 zr[2], zi[2];
#pragma unroll
        for (int p = 0; p < 2; p++)
#pragma unroll
            for (int i = 0; i < 4; i++) {
                const uint32_t r = dr[8 * c + 4 * p + i], m = di[8 * c + 4 * p + i], tr = u4(tw[p], i), ti = u4(tw[2 + p], i);
                if (SHEAR) {
                    const uint32_t r1 = hfma(tr, m, r), m1 = hfma(ti, r1, m);
                    u4r(zr[p], i) = hfma(tr, m1, r1); u4r(zi[p], i) = m1;
                } else {
                    u4r(zr[p], i) = hfms(m, ti, hmul(r, tr));
                    u4r(zi[p], i) = hfma(m, tr, hmul(r, ti));
                }
            }
        wg_fence();
        wgmma_h32_rs<0>(X[c][0], zi[0], d2 + 2, 0);
        wgmma_h32_rs<0>(X[c][1], zi[1], d2 + 6, 0);
        wgmma_h32_rs<0>(X[c][0], zr[0], d2, 1);
        wgmma_h32_rs<0>(X[c][1], zr[1], d2 + 4, 1);
        wg_commit();
    }
}

template <int NC, class Idle, class Staged>
__device__ __forceinline__ void conv_wg(int ch0, int layer, uint32_t eo, uint32_t zb, uint32_t s23, uint32_t kexp, uint32_t epoch, uint32_t st, uint32_t sbar, uint32_t fbar,
                                        int warp, int lane, uint4 (&a1)[4], uint4 (&tw)[4], Idle idle, Staged staged TS_ARG) {
    const int wg = warp >> 2, w = warp & 3, t = 32 * w + lane, mi = lane >> 3, mj = lane & 7;
    auto F = [](uint32_t x) { return __uint_as_float(x); };
    uint32_t KH[NC][2][8];
    TS(2);
    fft_forward<NC, false>(a1, tw, eo, s23, KH, [] {});
    named_bar(1 + wg, 128);
    uint4 a4[4];
#pragma unroll
    for (int i = 0; i < 4; i++) if (NC == 2) { tw[i] = ldg_tab(4 + i, t); a4[i] = ldg_tab(12 + i, t); }
    wg_wait<0>();
    TS(4);
    idle();
    uint2 x[NC][2][2];
    const uint32_t ra[2] = {4u * t, 4u * (t ^ 252)};
    auto stats = [&] {
        uint4 s[8];
        TS(1);
#pragma unroll
        for (int i = 0; i < 8; i++) s[i] = make_uint4(layer, 0, 0, 0);
        int spin = 0;
        uint32_t bad;
        do {
            bad = 0;
#pragma unroll
            for (int i = 0; i < 8; i++)
                if (((s[i].x ^ layer) & 1u) == 0) s[i] = ld_ll4((const uint4*)(g_fs[0] + ra[i >> 2] + (SEQ * (i & 1) + 1024 * ((i >> 1) & 1))));
#pragma unroll
            for (int i = 0; i < 8; i++) bad |= ~(s[i].x ^ layer);
        } while ((bad & 1u) && ++spin < (1 << 18));
#pragma unroll
        for (int i = 0; i < 8; i++) sts128(st + i * 2048 + t * 16, s[i]);
        __syncwarp();
        if (lane == 0) mbar_arrive(sbar + 8 * w);
        TS(14);
    };
    {
        const int tile = ((2 * w + (lane & 1)) ^ ((lane & 2) ? 15 : 0)) + 4 * (lane & 4);
        const bf16* pp = g_x1T + (uint32_t)(ch0 + NC - 1) * XP + 64 * tile + 60;
        uint32_t v;
        int spin = 0;
        do { asm volatile("ld.relaxed.gpu.global.u32 %0, [%1];" : "=r"(v) : "l"(pp) : "memory"); } while (__any_sync(~0u, ~(v ^ layer) & 1u) && ++spin < HINT_SPINS);
    }
    TS(5);
    auto xload = [&](int i) {
        const unsigned long long v = ld_ll((const unsigned long long*)(g_x1T + (uint32_t)ch0 * XP + ra[(i >> 1) & 1] + ((i >> 2) * XP + 1024 * (i & 1))));
        x[i >> 2][(i >> 1) & 1][i & 1] = make_uint2((uint32_t)v, (uint32_t)(v >> 32));
    };
#pragma unroll
    for (int i = 0; i < 4 * NC; i++) xload(i);
    TS(6);
    if (NC == 1) stats();
    for (int spin = 0; spin < (1 << 18); spin++) {
        uint32_t bad = 0;
#pragma unroll
        for (int i = 0; i < 4 * NC; i++) bad |= ~(x[i >> 2][(i >> 1) & 1][i & 1].x ^ layer);
        if (!(bad & 1u)) break;
#pragma unroll
        for (int i = 0; i < 4 * NC; i++) if (((x[i >> 2][(i >> 1) & 1][i & 1].x ^ layer) & 1u) == 0) xload(i);
    }
    __syncwarp();
#pragma unroll
    for (int i = 0; i < 4; i++) if (NC == 1) { tw[i] = ldg_tab(4 + i, t); a4[i] = ldg_tab(12 + i, t); }
    TS(26);
    if (NC == 2) mbar_wait(sbar + 8 * w, 0);
    staged();
    {
        uint4 s[2][2][2];
        uint32_t u[NC][2][4];
#pragma unroll
        for (int h = 0; h < 2; h++) {
            if (NC == 1 || h == 0) {
#pragma unroll
                for (int i = 4 * h; i < (NC == 1 ? 4 * h + 4 : 8); i++) s[i >> 2][(i >> 1) & 1][i & 1] = lds128(st + i * 2048 + t * 16);
            }
            if (h == 0) TS(7);
#pragma unroll
            for (int c = 0; c < NC; c++)
#pragma unroll
                for (int j = 0; j < 4; j++) {
                    const uint4 &a = s[h][j >> 1][0], &b = s[h][j >> 1][1];
                    const uint32_t xv = (j & 1) ? x[c][h][j >> 1].y : x[c][h][j >> 1].x;
                    u[c][h][j] = pack2h(fmaf(bf_lo(xv), F(u4(a, 2 * (j & 1))), F(u4(b, 2 * (j & 1)))), fmaf(bf_hi(xv), F(u4(a, 2 * (j & 1) + 1)), F(u4(b, 2 * (j & 1) + 1))));
                }
        }
#pragma unroll
        for (int c = 0; c < NC; c++) fft_stage<NC>(u[c], c, eo, w, lane);
    }
    TS(8);
    fence_async_smem();
    TS(9);
    named_bar(1 + wg, 128);
    uint32_t X[NC][2][8], Y[NC][2][8];
    uint32_t oscale[NC];
    fft_forward<NC, true>(a1, tw, eo, s23, X, [&] {
#pragma unroll
        for (int c = 0; c < NC; c++) oscale[c] = (lds32(kexp + 4 * c) + 3u) * 0x00800080u;
        if (layer) {
#pragma unroll
            for (int i = 0; i < 4 * NC; i++) asm volatile("mov.b32 %0, 0;\nmov.b32 %1, 0;" : "=r"(x[i >> 2][(i >> 1) & 1][i & 1].x), "=r"(x[i >> 2][(i >> 1) & 1][i & 1].y));
        }
        if (NC == 2 && wg == 1 && lane == 0) mbar_arrive(fbar);
        TS(3); if (F_STAG >= 2 && NC == 2 && wg == 1) named_bar(10 + w, 64); });
    if (F_STAG == 2 && NC == 2 && wg == 0) asm volatile("bar.arrive %0, 64;" ::"r"(10 + w) : "memory");
    TS(10);
    const uint64_t d3 = mkdesc(s23 + 4096, 16, 1024, 1);
#pragma unroll
    for (int c = 0; c < NC; c++) {
        wg_wait<NC - 1>();
        TS(11 + c);
        uint4 pr[2], pi[2];
#pragma unroll
        for (int i = 0; i < 4; i++) {
            const uint32_t er = X[c][0][i], ei = X[c][0][4 + i], orr = X[c][1][i], oi = X[c][1][4 + i];
            const uint32_t ar = KH[c][0][i], ai = KH[c][0][4 + i], br = KH[c][1][i], bi = KH[c][1][4 + i];
            u4r(pr[0], i) = hfms(bi, oi, hfma(br, orr, hfms(ai, ei, hmul(ar, er))));
            u4r(pi[0], i) = hfma(bi, orr, hfma(br, oi, hfma(ai, er, hmul(ar, ei))));
            u4r(pr[1], i) = hfms(ai, oi, hfma(ar, orr, hfms(bi, ei, hmul(br, er))));
            u4r(pi[1], i) = hfma(ai, orr, hfma(ar, oi, hfma(bi, er, hmul(br, ei))));
        }
        if (F_STAG == 3 + c && NC == 2 && wg == 0) asm volatile("bar.arrive %0, 64;" ::"r"(10 + w), "r"(pr[0].x ^ pr[1].w ^ pi[0].y ^ pi[1].z) : "memory");
        wg_fence();
        wgmma_h32_rs<0>(Y[c][0], pr[0], d3, 0);
        wgmma_h32_rs<0>(Y[c][1], pr[1], d3 + 4, 0);
        wgmma_h32_rs<0>(Y[c][0], pi[0], d3 + 2, 1);
        wgmma_h32_rs<0>(Y[c][1], pi[1], d3 + 6, 1);
        wg_commit();
    }
#pragma unroll
    for (int c = 0; c < NC; c++) {
        if (c + 1 < NC) wg_wait<1>(); else wg_wait<0>();
        TS(13 + c);
        uint32_t zr[2][4], zi[2][4];
#pragma unroll
        for (int p = 0; p < 2; p++)
#pragma unroll
            for (int i = 0; i < 4; i++) {
                const uint32_t r = Y[c][p][i], m = Y[c][p][4 + i], tr = u4(tw[p], i), ti = u4(tw[2 + p], i);
                const uint32_t r1 = hfms(tr, m, r), m1 = hfms(ti, r1, m);
                zr[i & 1][2 * p + (i >> 1)] = hfms(tr, m1, r1);
                zi[i & 1][2 * p + (i >> 1)] = m1;
            }
        const int kr = 4 * (mj >> 1) + (mj & 1) + 2 * (mj >> 2), ki = kr ^ 2;
#pragma unroll
        for (int h = 0; h < 2; h++) {
            const uint32_t a = zb + (2 * w + h) * 2048;
            stsm_x4(a + ki * 128 + (((4 * c + mi) ^ (ki & 7)) << 4), zi[h][0], zi[h][1], zi[h][2], zi[h][3]);
            stsm_x4(a + kr * 128 + (((4 * c + mi) ^ (kr & 7)) << 4), zr[h][0], zr[h][1], zr[h][2], zr[h][3]);
        }
    }
    TS(15);
    fence_async_smem();
    TS(16);
    named_bar(1 + wg, 128);
    TS(17);
    float acc[16 * NC];
    const uint64_t dz = mkdesc(zb, 4096, 1024, 1);
    wg_fence();
#pragma unroll
    for (int ks = 0; ks < 4; ks++) wgmma_s4(acc, a4[ks], dz + ks * 256, 0x44EEEE44u, ks > 0);
    wg_commit();
    const uint32_t fb = ~lds32(epoch);
    uint32_t mk[NC][2][4];
    const char* dst[2];
    {
        uint32_t l2;
        asm volatile("mov.u32 %0, %%laneid;" : "=r"(l2));
        const char* base = layer ? (const char*)g_of + (uint32_t)(ch0 / 80) * 327680u + (uint32_t)(ch0 % 80) * 256u : (const char*)g_x2T + (uint32_t)ch0 * (XP * 2u);
        const uint32_t k0 = layer ? 8 : (ch0 >> 1) & 3;
        uint32_t m0[2] = {k0 == 2 * (l2 & 3), k0 == 2 * (l2 & 3) + 1}, m1[2][2];
#pragma unroll
        for (int h = 0; h < 2; h++) {
            const uint32_t v = (32 * w + l2) ^ (h ? 252u : 0u);
            dst[h] = base + (layer ? (v >> 4) * 20480u + (v & 15u) * 16u : v * 8u);
            m1[h][0] = m0[0] | (~(v >> 3) & layer); m1[h][1] = m0[1] | ((v >> 3) & layer);
            asm volatile("" : "+l"(dst[h]), "+r"(m1[h][0]), "+r"(m1[h][1]), "+r"(m0[h]), "+r"(oscale[h % NC]));
        }
#pragma unroll
        for (int i = 0; i < 8 * NC; i++) {
            const int c = i >> 3, h = (i >> 2) & 1, j = i & 3;
            mk[c][h][j] = (j >> 1) == (NC == 2 ? c : ch0 & 1) ? m1[h][j & 1] : m0[j & 1];
            if (NC == 1) asm volatile("" : "+r"(mk[c][h][j]));
        }
        mbar_wait(sbar, 0);
    }
    auto mark = [&](uint32_t v, uint32_t m) { return (v & ~m) | (fb & m); };
    wg_wait<0>();
    TS(18);
#pragma unroll
    for (int c = 0; c < NC; c++) {
        uint32_t r[2][4];
#pragma unroll
        for (int j = 0; j < 4; j++) {
            const float* d = acc + 4 * (4 * c + j);
            const uint32_t y0 = pack2(d[0] + d[2], d[1] + d[3]), y1 = pack2(d[0] - d[2], d[1] - d[3]);
            asm("fma.rn.bf16x2 %0, %1, %2, %3;" : "=r"(r[0][j]) : "r"(y0), "r"(oscale[c]), "r"((j & 1) ? x[c][0][j >> 1].y : x[c][0][j >> 1].x));
            asm("fma.rn.bf16x2 %0, %1, %2, %3;" : "=r"(r[1][j]) : "r"(y1), "r"(oscale[c]), "r"((j & 1) ? x[c][1][j >> 1].y : x[c][1][j >> 1].x));
        }
#pragma unroll
        for (int h = 0; h < 2; h++)
            asm volatile("{\n.reg .pred p;\n.reg .b128 t;\n.reg .b64 a, b;\nsetp.ne.u32 p, %5, 0;\nmov.b64 a, {%1, %2};\nmov.b64 b, {%3, %4};\nmov.b128 t, {a, b};\n"
                         "@p st.relaxed.gpu.global.b128 [%0], t;\n@!p st.relaxed.gpu.global.b64 [%6], a;\n@!p st.relaxed.gpu.global.b64 [%6 + 2048], b;\n}"
                         ::"l"(dst[h] + c * 256), "r"(mark(r[h][0], mk[c][h][0])), "r"(mark(r[h][1], mk[c][h][1])), "r"(mark(r[h][2], mk[c][h][2])), "r"(mark(r[h][3], mk[c][h][3])), "r"(layer), "l"(dst[h] + c * XP * 2) : "memory");
    }
    if (layer == 0 && lane == 0) asm volatile("red.relaxed.gpu.global.add.u32 [%0], %1;" ::"l"(g_xcnt[ch0 >> 6][w]), "n"(NC) : "memory");
    TS(19);
}

#define Q_S0 8
#define R_CONS 192
#define K_CSUN 1
constexpr int K_CSU = K_CSUN;
#define G_MAP 1
constexpr int Q_SP = 4;
#define A_VLO 4
constexpr int Q_ST = 4;
constexpr int Q_AB = 16384, Q_BB = 30720, Q_SB = Q_AB + Q_BB;
constexpr int Q_EROW = 336;
constexpr int Q_ESLOT = 8 * Q_EROW;
constexpr int Q_EOFF = Q_ST * Q_SB;
constexpr int Q_KG = 2 * Q_SB;
static_assert(3 * Q_ESLOT <= 8192 && Q_KG + KG_TABLES <= Q_EOFF + 4096, "exchange slots, kernel generation");
constexpr int F_EO = Q_EOFF, F_S23 = F_EO + 2 * 8192 + 4096, Q_KDUMP = F_S23 + 8192;
constexpr int Q_MISC = Q_KDUMP + 6 * KG_RES;
__host__ __device__ constexpr int w_grp(int j) { return j < 7 ? 2 * Q_SB + 4096 + j * 12800 : 0; }
constexpr int W_RES = Q_AB;
__device__ __forceinline__ int o_slot(int wg, int s) { return W_RES + (((2 * s + 2) & 7) + wg) * 10240; }
__device__ __forceinline__ int w_out(int wg) { return W_RES + (2 + 3 * wg) * 10240; }
static_assert(W_RES + 8 * 10240 == w_grp(0) && w_grp(6) + 12800 <= Q_EOFF && w_grp(3) <= 3 * Q_SB, "phase W layout");

constexpr int Q_WOT = Q_EOFF + 4096;

__device__ unsigned g_epoch;
__device__ __align__(1024) unsigned g_bar[4][16][32];
__device__ __align__(1024) uint4 g_wop[8][80][10][8];
__device__ __align__(1024) uint4 g_csp[8][16][96];
__device__ __align__(1024) uint4 g_stp[16][8][64];
__device__ __align__(1024) uint4 g_sp2[16][8][8][8];
__device__ __align__(1024) uint4 g_halo[128][2][5][32];

struct Bars { uint64_t full[Q_ST], empty[Q_ST], wfull[3], ex[7], res, go, qdone, prep, hdone, idx, fdone0, att[2], wfree, soon[2], fdone1, st[4], kfree, staged, xland[4], spec; };
constexpr int NBAR = sizeof(Bars) / 8;
struct OBars { uint64_t full[8], ready[8], empty[8]; };
struct Misc { float cs[240], mean[2][64], rstd[2][72]; Bars bar[2]; OBars ob; KgShared kg; uint32_t epoch, pad; };
#define MISC(f) (sb + Q_MISC + (uint32_t)offsetof(Misc, f))
constexpr int Q_SMEM = Q_MISC + sizeof(Misc) + TS_SMEM;
__host__ __device__ constexpr int bar_count(int i) {
#define BAR_IS(f) (i == offsetof(Bars, f) / 8)
    return (i >= 4 && i < 8) ? 16 : (BAR_IS(go) || (i >= offsetof(Bars, att) / 8 && i < offsetof(Bars, st) / 8)) ? 4 : (BAR_IS(qdone) || BAR_IS(fdone0)) ? 8 : BAR_IS(prep) ? 96 :
           BAR_IS(hdone) ? 6 : BAR_IS(kfree) ? 24 : BAR_IS(staged) ? 2 : 1;
}
__device__ __forceinline__ void grid_wait(const unsigned* c, int n, unsigned target, int lane) {
    const unsigned* p = c + 32 * min(lane, n - 1);
    unsigned v;
    int spin = 0;
    do { asm volatile("ld.relaxed.gpu.global.u32 %0, [%1];" : "=r"(v) : "l"(p) : "memory"); } while (!__all_sync(~0u, (int)(v - target) >= 0) && ++spin < (1 << 18));
    fence_acquire();
}
__device__ __forceinline__ void grid_arrive(unsigned* c) {
    fence_release();
    asm volatile("red.relaxed.gpu.global.add.u32 [%0], 1;" ::"l"(c) : "memory");
}

#define TMAP(n) ([] { const CUtensorMap* p_; asm volatile("{\n.reg .b64 t;\nmov.b64 t, fused_kernel_param_" #n ";\ncvta.param.u64 %0, t;\n}" : "=l"(p_)); return p_; }())
extern "C" __global__ void __launch_bounds__(384, 1)
fused_kernel(const SsmParams sp, const __grid_constant__ CUtensorMap mX0, const __grid_constant__ CUtensorMap mX1, const __grid_constant__ CUtensorMap mW,
             const __grid_constant__ CUtensorMap mWr,
             const __grid_constant__ CUtensorMap mRes0, const __grid_constant__ CUtensorMap mRes1, const __grid_constant__ CUtensorMap mOut,
             const __grid_constant__ CUtensorMap mWo, const __grid_constant__ CUtensorMap mFin, const __grid_constant__ CUtensorMap mResA) {
    extern __shared__ __align__(1024) char smraw[];
    const uint32_t sb = s2u(smraw);
    int tid, warp, lane, bx, rank, blk, hg, rot, c0;
    int role;
    {
        const int c = blockIdx.x >> 1, d = c - 41, r = d >= 21 ? 3 : d >= 14 ? 2 : d >= 7 ? 1 : 0;
        const int gp = c < 4 ? 0 : c <= 40 ? (c + 7) & 7 : d - 7 * r + 1;
        const int k = c < 4 ? c : c <= 40 ? (c >> 3) + (gp == 0 ? 3 : gp >= 3 && gp < 7 ? 0 : -1) : (gp >= 3 ? 5 : 4) + r;
        role = G_MAP == 1 ? 16 * k + 2 * gp + (blockIdx.x & 1) : G_MAP == 2 ? 16 * gp + 2 * k + (blockIdx.x & 1) : blockIdx.x;
    }
    auto indices = [&] {
        asm volatile("mov.u32 %0, %%tid.x;" : "=r"(tid));
        asm volatile("mov.u32 %0, %1;" : "=r"(bx) : "r"(role));
        warp = __shfl_sync(~0u, tid >> 5, 0); lane = tid & 31;
        rank = bx & 1; blk = bx & 15; hg = bx >> 4;
        const int u = ((blk >> 1) + hg) & 7;
        rot = (5 * u) >> 2; c0 = 16 * (u & 3);
    };
    indices();
    TS_DECL;
    TS_BEGIN;
#define EPOCH lds32(MISC(epoch))
    int layer = 0;
    uint32_t bars = MISC(bar);
#define BAR(f) (bars + (uint32_t)offsetof(Bars, f))
    auto chunk = [&](int it, int s0) {
        const int i = it < s0 ? it : it - 2;
        return (it >> 1) == (s0 >> 1) ? rot + (it & 1) : i < rot ? i : i + 2;
    };
    auto osrc_of = [&](int j) { return j == 0 ? hg : j - 1 < hg ? j - 1 : j; };
    auto issue_w = [&](uint32_t bb, int it, int lay) {
        const int half = rank;
        const int s = it & (Q_ST - 1);
        const uint32_t fb = bb + 8 * s, db = sb + s * Q_SB + Q_AB + half * 15360;
        const int k0 = chunk(it, Q_SP * lay) * 64 + half * 32;
#pragma unroll
        for (int p = 0; p < 3; p++) tma2d_mc(db + p * 4096, TMAP(3), p * DM + hg * 80, k0, fb, 3);
        tma3d_mc(db + 12288, TMAP(4), hg * 80 + 64, k0, 0, fb, 3);
    };
    auto issue_x = [&](int it) {
        const int s = it & (Q_ST - 1), kc = chunk(it, Q_SP * layer);
        mbar_expect(BAR(full) + 8 * s, Q_SB);
        tma3d(sb + s * Q_SB, TMAP(1) + layer, (layer ? blk : kc) * 64, (layer ? kc : blk) * 64, 0, BAR(full) + 8 * s);
    };
    {
        KgParams kp;
        const uint32_t epoch0 = ldg32(sp.epoch);
        kgen_load(kp, bx, warp, lane, sp);
        if (warp < 8) {
            cluster_arrive_relaxed();
        } else {
            if (elect_one()) {
                if (warp < 10) { prefetch_tmap(TMAP(3)); prefetch_tmap(TMAP(4)); } else prefetch_tmap(warp == 10 ? TMAP(1) : TMAP(8));
                const uint32_t b0 = bars + (warp >= 10 ? sizeof(Bars) : 0);
                if (warp & 1) {
#pragma unroll
                    for (int i = 0; i < NBAR / 2; i++) mbar_init(b0 + i * 8, bar_count(i));
                } else {
#pragma unroll
                    for (int i = NBAR / 2; i < NBAR; i++) mbar_init(b0 + i * 8, bar_count(i));
                }
                fence_mbar_init();
            }
            __syncwarp();
            cluster_arrive_relaxed();
            TS(29);
            cluster_wait();
            TS(27);
            if (elect_one()) {
                if (warp < 10) {
                    issue_w(BAR(full), warp - 8, 0);
                } else if (warp == 10) {
                    issue_x(0); issue_x(1);
                    prefetch_l2((const char*)c_fft + bx * (sizeof(c_fft) / 128), sizeof(c_fft) / 128);
                } else {
                    mbar_expect(BAR(idx), 8192 + 6400);
                    asm volatile("cp.async.bulk.tensor.4d.shared::cluster.global.mbarrier::complete_tx::bytes [%0], [%1, {0, 0, %3, %4}], [%2];"
                                 ::"r"(sb + Q_WOT), "l"(TMAP(8)), "r"(BAR(idx)), "r"(10 * hg), "r"(5 * blk) : "memory");
                    bulk_g2s(sb + F_S23, c_fft + 18 * 512, 8192, BAR(idx));
                }
            }
            __syncwarp();
            TS(30);
        }
        indices();
        kgen_tables(kp, sb + Q_KG, sb + Q_KDUMP, MISC(kg), warp, lane, [&] { if (warp < 8) cluster_wait(); } TS_PASS);
        __syncwarp();
        if (lane == 0) { mbar_arrive_cta(BAR(kfree), 0); mbar_arrive_cta(BAR(kfree), 1); }
        if (warp >= 8) {
            const int t2 = tid - 256;
            float csum[10];
            if (warp < 11 && elect_one()) {
#pragma unroll
                for (int i = 0; i < 8; i++) mbar_init(MISC(ob) + (warp - 8) * 64 + i * 8, warp == 10 ? 4 : 1);
                fence_mbar_init();
            }
            __syncwarp();
            if (t2 == 0) sts32(MISC(epoch), epoch0);
            if (t2 < 64) stg128(&g_sp2[blk][hg][0][0] + t2, make_uint4(0, 0, 0, 0));
            if (t2 >= 64 && t2 < 80) stg128(&g_of[hg][blk][640 * ((t2 >> 3) & 1) + 8 * (73 + (t2 & 6)) + 6 + (t2 & 1)], make_uint4(epoch0, epoch0, epoch0, epoch0));
            if (t2 >= 120) stg128((uint4*)g_fs + 8 * bx + t2 - 120, make_uint4(0, 0, 0, 0));
#pragma unroll
            for (int i = 0; i < 2; i++)
                if (t2 + 128 * i < 192) stg128(g_x1T + (uint32_t)cta_channel(bx, 4 * i + 1 + 2 * (t2 >> 6)) * XP + 32 * (t2 & 62) + 48 + 8 * (t2 & 1), make_uint4(0, 0, 0, 0));
#pragma unroll
            for (int i = 0; i < 3; i++)
                if (t2 + 128 * i < 320) stg128(&g_halo[bx][0][0][0] + t2 + 128 * i, make_uint4(0, 0, 0, 0));
            named_bar(13, 128);
            if (warp > 8) {
                const int hw = warp - 9, mi = lane >> 3, mj = lane & 7;
                mbar_wait(BAR(idx), 0);
                if (hw == 2 && elect_one()) { bulk_s2g(&g_wop[hg][5 * blk], sb + Q_WOT, 6400); bulk_commit(); }
                __syncwarp();
                mbar_wait(BAR(full), 0);
                mbar_wait(BAR(full) + 8, 0);
#pragma unroll
                for (int f = 0; f < 10; f++) csum[f] = 0.f;
#pragma unroll K_CSU
                for (int G = 0; G < 5; G++) {
                    const int row = c0 + 40 * rank + 8 * G + mj;
                    const uint32_t b = sb + (row >> 6) * Q_SB + Q_AB + ((row >> 5) & 1) * 15360;
                    uint32_t r[10];
                    ldsm_x4_t(r[0], r[1], r[2], r[3], b + hw * 4096 + (row & 31) * 128 + ((mi ^ mj) << 4));
                    ldsm_x4_t(r[4], r[5], r[6], r[7], b + hw * 4096 + (row & 31) * 128 + (((4 + mi) ^ mj) << 4));
                    ldsm_x2_t(r[8], r[9], b + 12288 + hw * 1024 + (row & 31) * 32 + (((mi & 1) ^ (mj >> 2)) << 4));
#pragma unroll
                    for (int f = 0; f < 10; f++) csum[f] += bf_lo(r[f]) + bf_hi(r[f]);
                }
                const int q = lane & 3;
                float t[3];
#pragma unroll
                for (int j = 0; j < 3; j++) {
                    float v[4];
#pragma unroll
                    for (int k = 0; k < 4; k++) v[k] = 4 * j + k < 10 ? csum[4 * j + k] : 0.f;
                    const float a0 = ((q & 2) ? v[2] : v[0]) + __shfl_xor_sync(~0u, (q & 2) ? v[0] : v[2], 2);
                    const float a1 = ((q & 2) ? v[3] : v[1]) + __shfl_xor_sync(~0u, (q & 2) ? v[1] : v[3], 2);
                    t[j] = ((q & 1) ? a1 : a0) + __shfl_xor_sync(~0u, (q & 1) ? a0 : a1, 1);
                }
                st_ll4(&g_csp[hg][blk][tid - 288], ~EPOCH & 1u, __float_as_uint(t[0]), __float_as_uint(t[1]), __float_as_uint(t[2]));
            }
        }
        TS(1);
    }

    uint4 fa1[4], ftw[4];
    auto conv_tables = [&] {
#pragma unroll
        for (int i = 0; i < 4; i++) { fa1[i] = ldg_tab(i, tid & 127); ftw[i] = ldg_tab(8 + i, tid & 127); }
    };
    if (warp >= 8) {
    asm volatile("setmaxnreg.dec.sync.aligned.u32 %0;" ::"n"(504 - 2 * R_CONS));
    uint32_t ophase = 0;
#pragma unroll 1
    for (; layer < 2; layer++, bars += sizeof(Bars)) {
        indices();
        TS_PHASE(2 * layer);
        if (layer) {
            const int i = warp - 8, g = lane >> 2;
            const uint32_t eb = ~EPOCH, a = sb + i * Q_SB + g * 128 + (((2 * (lane & 3)) ^ g) << 4) + 2 * (g & 6);
            const unsigned* pp = g_xcnt[chunk(i, Q_SP)][(blk < 8 ? blk : 15 - blk) >> 1];
            mbar_wait(BAR(fdone0) - sizeof(Bars), 0);
            if (i == 3) mbar_wait(BAR(fdone1) - sizeof(Bars), 0);
            if (i == 3 && elect_one()) grid_arrive(g_bar[2][hg]);
            __syncwarp();
            uint32_t bad;
            int spin = 0;
            do { asm volatile("ld.relaxed.gpu.global.u32 %0, [%1];" : "=r"(bad) : "l"(pp) : "memory"); } while ((int)(bad + 64 * eb) < 0 && ++spin < HINT_SPINS);
            fence_async_global();
            TS(1);
            spin = 0;
            do {
                if (elect_one()) {
                    mbar_expect(BAR(xland) + 8 * i, Q_AB);
                    tma3d(sb + i * Q_SB, TMAP(2), blk * 64, chunk(i, Q_SP) * 64, 0, BAR(xland) + 8 * i);
                }
                __syncwarp();
                mbar_wait(BAR(xland) + 8 * i, spin & 1);
                bad = 0;
#pragma unroll
                for (int k = 0; k < 16; k++) bad |= lds32(a + k * 1024) ^ eb;
            } while (__any_sync(~0u, bad & 1u) && ++spin < (1 << 16));
            if (lane == 0) mbar_expect(BAR(full) + 8 * i, Q_BB);
            TS(9);
        }
        if (warp == 8) {
            if (layer) {
                grid_wait(g_bar[2][0], 8, 16 * (EPOCH + 1), lane);
                fence_async_global();
                TS(10);
            }
            if (elect_one()) {
#pragma unroll 1
                for (int it = 2 + 2 * layer; it < 10; it++) {
                    if (it >= Q_ST) mbar_wait(BAR(empty) + 8 * (it & (Q_ST - 1)), ((it >> 2) - 1) & 1);
                    else mbar_wait(BAR(kfree), 0);
                    if (it == Q_ST + Q_SP * layer) mbar_wait(BAR(hdone), 0);
                    issue_x(it);
                    issue_w(BAR(full), it, layer);
                    if (it == Q_SP + 1) mbar_arrive(BAR(spec));
                }
                { prefetch_tmap(TMAP(5) + layer); prefetch_tmap(TMAP(7)); prefetch_tmap(TMAP(10)); }
                if (layer == 0) { mbar_wait(BAR(prep), 0); fence_async_global(); }
#pragma unroll 1
                for (int j = 0; j < 8; j++) {
                    const int b = (j + 1) >> 2;
                    const uint32_t fb = BAR(wfull) + 8 * b;
                    if (j == 0 || j == 3 || j == 7) {
                        mbar_wait(BAR(empty) + 8 * ((2 + b) & 3), b < 2);
                        TS(11 + b);
                        mbar_expect(fb, (b == 0 ? 3 : b == 1 ? 4 : 1) * 12800);
                    }
                    bulk_g2s_mc(sb + w_grp(j) + rank * 6400, &g_wop[hg][osrc_of(j) * 10 + rank * 5], 6400, fb, 3);
                }
                mbar_expect(BAR(res), 20480);
                if (layer) {
                    tma3d(sb + W_RES, TMAP(6), blk * 64, hg * 80, 0, BAR(res));
                } else {
#pragma unroll 1
                    for (int p = 0; p < 2; p++) {
                        tma3d(sb + W_RES + p * 10240, TMAP(10), hg * 80, blk * 64, p, BAR(res));
                        tma3d(sb + W_RES + p * 10240 + 8192, TMAP(5), hg * 80 + 64, blk * 64, p, BAR(res));
                    }
                }
            }
            __syncwarp();
        } else {
            const int ht = tid - 288, hw = warp - 9, mi = lane >> 3, mj = lane & 7, g = lane >> 2, q = lane & 3;
            auto F = [](uint32_t x) { return __uint_as_float(x); };
            auto U = [](float x) { return __float_as_uint(x); };
            const uint32_t lb = layer ^ 1, eb = ~EPOCH & 1u;
            if (layer) mbar_wait(BAR(spec), 0);
            mbar_wait(BAR(full), layer);
            mbar_wait(BAR(full) + 8, layer);
            if (ht == 0) TSX(2, 2);
            uint32_t xf[3][20];
#pragma unroll
            for (int i = 0; i < 3; i++) {
                const int tile = min(hw + 3 * i, 7);
#pragma unroll
                for (int k = 0; k < 5; k++) {
                    const int ch = c0 + 16 * k + 8 * (mi >> 1), tok = 16 * (tile & 3) + 8 * (mi & 1);
                    const uint32_t a = sb + (ch >> 6) * Q_SB + (tile >> 2) * 8192;
                    if (layer == 0) ldsm_x4(xf[i][4 * k], xf[i][4 * k + 1], xf[i][4 * k + 2], xf[i][4 * k + 3], a + (tok + mj) * 128 + ((((ch & 63) >> 3) ^ mj) << 4));
                    else ldsm_x4_t(xf[i][4 * k], xf[i][4 * k + 1], xf[i][4 * k + 2], xf[i][4 * k + 3], a + ((ch & 63) + mj) * 128 + (((tok >> 3) ^ mj) << 4));
                }
            }
            fence_async_smem();
            __syncwarp();
            if (lane == 0) { mbar_arrive_cta(BAR(hdone), 0); mbar_arrive_cta(BAR(hdone), 1); }
            if (ht == 0) TSX(2, 3);
            if (layer == 0) {
                if (hw == 2 && elect_one()) { bulk_wait(); fence_async_global(); grid_arrive(g_bar[3][hg]); }
                __syncwarp();
                mbar_wait(BAR(kfree), 0);
            }
            if (ht == 0) TSX(2, 8);
#pragma unroll 1
            for (int tile = hw; tile < 8; tile += 3) {
                float a[4] = {0.f, 0.f, 0.f, 0.f};
#pragma unroll
                for (int j = 0; j < 20; j++) {
                    const float lo = bf_lo(xf[0][j]), hi = bf_hi(xf[0][j]);
                    a[2 * (j & 1)] += lo + hi; a[2 * (j & 1) + 1] = fmaf(lo, lo, fmaf(hi, hi, a[2 * (j & 1) + 1]));
                    xf[0][j] = xf[1][j]; xf[1][j] = xf[2][j];
                }
#pragma unroll
                for (int j = 0; j < 4; j++) { a[j] += __shfl_xor_sync(~0u, a[j], 1); a[j] += __shfl_xor_sync(~0u, a[j], 2); }
                if (q == 0) st_ll4(&g_stp[blk][hg][8 * tile + g], (U(a[0]) & ~1u) | lb, U(a[1]), U(a[2]), U(a[3]));
            }
            if (ht == 0) TSX(2, 4);
            if (layer == 0) {
                float t[4] = {0.f, 0.f, 0.f, 0.f};
                uint4 v[16];
                int spin = 0;
                uint32_t bad;
                do {
                    bad = 0;
#pragma unroll
                    for (int j = 0; j < 16; j++) v[j] = ld_ll4(&g_csp[hg][j][ht]);
#pragma unroll
                    for (int j = 0; j < 16; j++) bad |= v[j].x ^ eb;
                } while ((bad & 1u) && ++spin < (1 << 18));
#pragma unroll
                for (int j = 0; j < 16; j++) { t[0] += F(v[j].y); t[1] += F(v[j].z); t[2] += F(v[j].w); }
#pragma unroll
                for (int j = 0; j < 3; j++) if (q + 4 * j < 10) sts32(MISC(cs) + 4 * (80 * hw + 20 * (g >> 1) + 2 * (q + 4 * j) + (g & 1)), U(t[j]));
                if (hw == 2) grid_wait(g_bar[3][0], 8, 16 * (EPOCH + 1), lane);
            }
            if (ht == 0) TSX(2, 15);
            if (ht < 80) {
                const bool halo = ht >= 64;
                const int p = halo ? (ht >> 3) & 1 : ht >> 5, i = halo ? (ht & 7) - 8 : 8 + 2 * (ht & 24) + (ht & 7);
                const uint4* src = &g_stp[halo && blk ? blk - 1 : blk][0][halo ? 32 * p + 24 + (ht & 7) : ht];
                uint4 v[8];
                int spin = 0;
                uint32_t bad;
                do {
                    bad = 0;
#pragma unroll
                    for (int j = 0; j < 8; j++) v[j] = ld_ll4(src + 64 * j);
#pragma unroll
                    for (int j = 0; j < 8; j++) bad |= v[j].x ^ lb;
                } while ((bad & 1u) && ++spin < (1 << 18));
                float t[4] = {0.f, 0.f, 0.f, 0.f};
#pragma unroll
                for (int j = 0; j < 8; j++) { t[0] += F(v[j].x); t[1] += F(v[j].y); t[2] += F(v[j].z); t[3] += F(v[j].w); }
                const uint32_t s0 = ln_finish_packed(t[0], t[1]), s1 = ln_finish_packed(t[2], t[3]);
                const uint32_t am = MISC(mean) + 4 * (64 * p + i), ar = MISC(rstd) + 4 * (72 * p + i);
                if (!halo) { sts32(am - 32, U(bf_hi(s0))); sts32(am, U(bf_hi(s1))); sts32(ar, U(frcp(bf_lo(s0)))); }
                sts32(ar + 32, U(frcp(bf_lo(s1))));
            }
            fence_acquire();
            mbar_arrive(BAR(prep));
            if (ht == 0) TSX(2, 5);
        }
        __syncwarp();
        indices();
        {
            const uint4 ko[2] = {ldg_tab(16, tid & 127), ldg_tab(17, tid & 127)};
            conv_tables();
            kernel_stage<1>(ko, sb + Q_KDUMP + 4 * KG_RES, MISC(kg), 4, sb + F_EO + 2 * 8192, warp & 3, lane);
            fence_async_smem();
        }
        {
            const int p = warp & 1;
            const uint32_t fb = EPOCH ^ layer ^ 1, ob = MISC(ob) + 32 * p;
            auto fetch = [&](int j) {
                if (elect_one()) {
                    mbar_expect(ob + 8 * ((j - 1) & 3), 10240);
                    bulk_g2s(sb + o_slot(p, (j - 1) & 3), &g_of[osrc_of(j)][blk][640 * p], 10240, ob + 8 * ((j - 1) & 3));
                }
                __syncwarp();
            };
            if (warp < 10) {
                const uint32_t* pp = &g_of[osrc_of(1 + min(lane >> 2, 6))][blk][640 * p + 8 * (73 + 2 * (lane & 3)) + 7].x + 1 + 2 * (lane & 1);
                mbar_wait(BAR(qdone), 0);
                mbar_wait(BAR(att) + 8 * p, 0);
                uint32_t miss = ~0u;
                int spin = 0;
#pragma unroll 1
                for (int j = 1; j < 8; j++) {
                    while (((miss >> (4 * j - 4)) & 15u) && ++spin < HINT_SPINS) {
                        uint32_t v;
                        asm volatile("ld.relaxed.gpu.global.u32 %0, [%1];" : "=r"(v) : "l"(pp) : "memory");
                        miss = __ballot_sync(~0u, (v ^ fb) & 1u);
                        fence_async_global();
                    }
                    if (j == 1) TS(16);
                    if (j > 3) mbar_wait(ob + 128 + 8 * ((j - 1) & 3), layer);
                    fetch(j);
                }
                TS(17);
            } else {
#pragma unroll 1
                for (int j = 1, spin = 0; j < 8;) {
                    const int s = (j - 1) & 3;
                    mbar_wait(ob + 8 * s, (ophase >> s) & 1);
                    ophase ^= 1u << s;
                    const uint32_t a = sb + o_slot(p, s) + (lane >> 2) * 132 + (lane & 3) * 32;
                    uint32_t bad = 0;
#pragma unroll
                    for (int i = 0; i < 10; i++) bad |= lds32(a + i * 1024) ^ fb;
                    if (__any_sync(~0u, bad & 1u) && ++spin < (1 << 16)) { fetch(j); continue; }
                    if (lane == 0) mbar_arrive(ob + 64 + 8 * s);
                    j++;
                }
            }
        }
        TS_PHASE(2 * layer + 1);
        TS(0);
        indices();
        named_bar(3, 128);
        conv_wg<1>(cta_channel(bx, 4), layer, sb + F_EO + 2 * 8192, sb + 2 * Q_SB, sb + F_S23, MISC(kg.kexp) + 16, MISC(epoch), sb, BAR(st), 0,
                   warp, lane, fa1, ftw,
        [&] {
            if (warp == 9) {
                auto F = [](uint32_t x) { return __uint_as_float(x); };
                mbar_wait(BAR(soon) + 8 * (hg >> 2), 0);
                TS(23);
                const uint4* src = &g_sp2[blk][hg][0][0] + lane;
                uint4* dst = (uint4*)(g_fs[(lane >> 2) & 1] + 1024 * (hg >> 2) + 64 * blk + 16 * (hg & 3)) + (lane & 3);
                const bool up = lane & 8;
#pragma unroll 1
                for (int spin = 0; spin < (1 << 18); spin++) {
                    const uint4 a = ld_ll4(src), b = ld_ll4(src + 32);
                    const bool ok = !__any_sync(~0u, ~((a.x ^ layer) & (b.x ^ layer)) & 1u);
                    const float s0 = F(a.x) + F(b.x), q0 = F(a.y) + F(b.y), s1 = F(a.z) + F(b.z), q1 = F(a.w) + F(b.w);
                    float sm = (up ? s1 : s0) + __shfl_xor_sync(~0u, up ? s0 : s1, 8), sq = (up ? q1 : q0) + __shfl_xor_sync(~0u, up ? q0 : q1, 8);
                    sm += __shfl_xor_sync(~0u, sm, 16); sq += __shfl_xor_sync(~0u, sq, 16);
                    const float m = sm * (1.0f / DM), r = frsq(fmaxf(fmaf(sq, 1.0f / DM, fmaf(-m, m, 1e-5f)), 1e-5f));
                    const uint32_t v = __float_as_uint(lane & 16 ? -m * r : r);
                    const uint32_t v0 = __shfl_sync(~0u, v, 4 * lane), v1 = __shfl_sync(~0u, v, 4 * lane + 1), v2 = __shfl_sync(~0u, v, 4 * lane + 2), v3 = __shfl_sync(~0u, v, 4 * lane + 3);
                    if (ok && lane < 8) st_ll4(dst, (v0 & ~1u) | (layer ^ 1), v1, v2, v3);
                    if (ok) break;
                }
            }
            TS(25);
            mbar_wait(BAR(staged), 0);
        }, [&] {
            if (tid == 352) prefetch_tmap(layer ? TMAP(9) : TMAP(2));
        } TS_PASS);
        named_bar(3, 128);
        TS(20);
    }
    } else {
#pragma unroll 1
    for (; layer < 2; layer++, bars += sizeof(Bars)) {
    indices();
    TS_PHASE(2 * layer);
    const int wg = warp >> 2, w = warp & 3;
    const int mi = lane >> 3, mj = lane & 7, g = lane >> 2, q = lane & 3;
    TS(2);
    float acc[120];
#pragma unroll
    for (int i = 0; i < 120; i++) acc[i] = 0.f;
    auto release = [&](int it) {
        if (lane == 0) { mbar_arrive_cta(BAR(empty) + 8 * (it & (Q_ST - 1)), 0); mbar_arrive_cta(BAR(empty) + 8 * (it & (Q_ST - 1)), 1); }
    };
#pragma unroll 1
    for (int it = 0; it < 10; it++) {
        const int s = it & (Q_ST - 1);
        const uint32_t st = sb + s * Q_SB;
        const bool hold = wg == 1 && it == Q_S0;
        if (hold) {
            wg_wait<0>();
            release(it - 1);
            mbar_wait(BAR(go), 0);
        }
        mbar_wait(BAR(full) + 8 * (s), (it >> 2) & 1);
        if (it < 2) TS(3 + it);
        if (it == 6) TS(5);
        if (it == 9) TS(6);
        const uint64_t da = mkdesc(st + wg * 8192, 16, 1024, 1);
        const uint64_t db = mkdesc(st + Q_AB, 4096, 1024, 1);
        const uint64_t dr = mkdesc(st + Q_AB + 12288, 1024, 256, 3);
        if (layer == 0) {
            wg_fence();
#pragma unroll
            for (int ks = 0; ks < 4; ks++) {
                const int sc = 1;
                wgmma_n192<0, 1>(*(float(*)[96]) & acc[0], da + ks * 2, db + (ks >> 1) * 960 + (ks & 1) * 128, sc);
                wgmma_n48<0, 1>(*(float(*)[24]) & acc[96], da + ks * 2, dr + (ks >> 1) * 960 + (ks & 1) * 32, sc);
            }
            wg_commit();
        } else {
            wg_fence();
#pragma unroll
            for (int ks = 0; ks < 4; ks++) {
                const int sc = 1;
                wgmma_n192<1, 1>(*(float(*)[96]) & acc[0], da + ks * 128, db + (ks >> 1) * 960 + (ks & 1) * 128, sc);
                wgmma_n48<1, 1>(*(float(*)[24]) & acc[96], da + ks * 128, dr + (ks >> 1) * 960 + (ks & 1) * 32, sc);
            }
            wg_commit();
        }
        wg_wait<1>();
        if (it > 0 && !hold) release(it - 1);
    }
    if (wg == 0 && lane == 0) mbar_arrive(BAR(go));
    asm volatile("setmaxnreg.inc.sync.aligned.u32 %0;" ::"n"(R_CONS));
    mbar_wait(BAR(prep), 0);
    const uint32_t ob = layer ^ 1;
    const bool first = (blk == 0 && w == 0);
    const bool sel0 = (2 * q > g), sel1 = (2 * q + 1 > g);
    constexpr float SC = 0.22360679774997896f * 1.4426950408889634f;
    const float m0 = __uint_as_float(lds32(MISC(mean) + 4 * (16 * warp + g))), m1 = __uint_as_float(lds32(MISC(mean) + 4 * (16 * warp + g + 8)));
    uint4 cs[3][5];
    auto cs_load = [&](int p) {
#pragma unroll
        for (int i = 0; i < 5; i++) cs[p][i] = lds128(MISC(cs) + 4 * (80 * p + 20 * q + 4 * i));
    };
    cs_load(1); cs_load(2);
    wg_wait<0>();
    TS(7);
    if (lane == 0) mbar_arrive(BAR(qdone));
    uint32_t ql[10], qh[10], kl[10], kh[10], vl[10], vh[10];
    auto fold = [&](int p, int f, int h) {
        const int j = (f < 8) ? 8 * p + f : 24 + 2 * p + (f - 8);
        const float c0 = __uint_as_float(u4(cs[p][f >> 1], 2 * (f & 1))), c1 = __uint_as_float(u4(cs[p][f >> 1], 2 * (f & 1) + 1));
        const float m = h ? m1 : m0;
        return pack2(fmaf(-m, c0, acc[4 * j + 2 * h]), fmaf(-m, c1, acc[4 * j + 2 * h + 1]));
    };
#pragma unroll
    for (int f = 0; f < 10; f++) { vh[f] = fold(2, f, 1); if (f < A_VLO) vl[f] = fold(2, f, 0); }
#pragma unroll
    for (int f = 0; f < 10; f++) kh[f] = fold(1, f, 1);
#pragma unroll
    for (int f = 0; f < A_VLO; f++) asm volatile("" : "+r"(vl[f]));
    {
        const uint32_t mk = w == 3 ? 1u : 0u;
        auto mark = [&](uint32_t& v) { v = (v & ~mk) | (ob & mk); };
        mark(kh[0]); mark(kh[5]); mark(vh[0]); mark(vh[4]); mark(vh[8]);
    }
    if (w == 3) {
        uint4* hp = &g_halo[bx][wg][0][lane];
        st_ll4(hp, kh[0], kh[1], kh[3], kh[4]); st_ll4(hp + 32, kh[5], kh[6], kh[8], kh[9]);
        st_ll4(hp + 64, vh[0], vh[1], vh[2], vh[3]); st_ll4(hp + 96, vh[4], vh[5], vh[6], vh[7]);
        st_ll4(hp + 128, vh[8], vh[9], kh[2], kh[7]);
    } else {
        const uint32_t a = sb + Q_EOFF + wg * 8192 + w * Q_ESLOT + mj * Q_EROW + mi * 16;
        stsm_x4(a, kh[0], kh[1], kh[3], kh[4]);
        stsm_x4(a + 64, kh[5], kh[6], kh[8], kh[9]);
        stsm_x4(a + 128, vh[0], vh[1], vh[2], vh[3]);
        stsm_x4(a + 192, vh[4], vh[5], vh[6], vh[7]);
        stsm_x4(a + 256, vh[8], vh[9], kh[2], kh[7]);
        __syncwarp();
        if (lane == 0) mbar_arrive(BAR(ex) + 8 * warp);
    }
    TS(9);
    cs_load(0);
#pragma unroll
    for (int f = 0; f < 10; f++) { kl[f] = fold(1, f, 0); if (f >= A_VLO) vl[f] = fold(2, f, 0); }
#pragma unroll
    for (int f = 0; f < 10; f++) { ql[f] = fold(0, f, 0); qh[f] = fold(0, f, 1); }
    auto rs = [&](int i) { return __uint_as_float(lds32(MISC(rstd) + 4 * (72 * wg + 16 * w + i))); };
    const float kx0 = rs(2 * q + (sel0 ? 0 : 8)), kx1 = rs(2 * q + (sel1 ? 1 : 9)), ky0 = rs(2 * q + (sel0 ? 8 : 16)), ky1 = rs(2 * q + (sel1 ? 9 : 17));
    const float rx = SC * rs(8 + g), ry = SC * rs(16 + g), cx0 = rx * kx0, cx1 = rx * kx1, cy0 = ry * ky0, cy1 = ry * ky1;
    uint4 hv[5];
    const uint4* hp = &g_halo[bx - 1][wg][0][lane];
    auto prev = [&] {
        if (w > 0) {
            const uint32_t a = sb + Q_EOFF + wg * 8192 + (w - 1) * Q_ESLOT + mj * Q_EROW + mi * 16;
            mbar_wait(BAR(ex) + 8 * (warp - 1), 0);
            ldsm_x4(hv[0].x, hv[0].y, hv[0].z, hv[0].w, a);
            ldsm_x4(hv[1].x, hv[1].y, hv[1].z, hv[1].w, a + 64);
            ldsm_x4_t(hv[2].x, hv[2].y, hv[2].z, hv[2].w, a + 128);
            ldsm_x4_t(hv[3].x, hv[3].y, hv[3].z, hv[3].w, a + 192);
            ldsm_x2_t(hv[4].x, hv[4].y, a + 256);
            ldsm_x2(hv[4].z, hv[4].w, a + 288 - (lane >> 4) * 32);
        } else if (blk > 0) {
#pragma unroll
            for (int f = 0; f < 5; f++) hv[f] = ld_ll4(hp + 32 * f);
        } else {
#pragma unroll
            for (int f = 0; f < 5; f++) hv[f] = make_uint4(0, 0, 0, 0);
        }
    };
    uint32_t vt[10][2];
#pragma unroll
    for (int f = 0; f < 10; f++) { vt[f][0] = movm_t(vl[f]); vt[f][1] = movm_t(vh[f]); }
    prev();
    TS(10);
    auto FA = [](int h) { return h == 0 ? 0 : h == 1 ? 3 : h == 2 ? 5 : 8; };
    auto FH = [](int h) { return h < 2 ? 2 : 7; };
    const uint32_t pm = (sel0 ? 0xFFFFu : 0u) | (sel1 ? 0xFFFF0000u : 0u);
    auto softmax = [&](float x0, float x1, float k0, float k1) {
        float mx = fmaxf(x0, x1);
        mx = fmaxf(mx, __shfl_xor_sync(~0u, mx, 1));
        mx = fmaxf(mx, __shfl_xor_sync(~0u, mx, 2));
        x0 = ex2(x0 - mx); x1 = ex2(x1 - mx);
        float sx = x0 + x1;
        sx += __shfl_xor_sync(~0u, sx, 1);
        sx += __shfl_xor_sync(~0u, sx, 2);
        const float ix = frcp(sx);
        return pack2(x0 * k0 * ix, x1 * k1 * ix);
    };
    uint32_t qm[4][2], py[4];
    float sl[4][2];
#pragma unroll
    for (int h = 0; h < 4; h++) {
        const int fa = FA(h), fb = fa + 1, fh = FH(h);
        const bool mine = (h & 1) ? (q >= 2) : (q < 2);
        qm[h][0] = mine ? ql[fh] : 0u; qm[h][1] = mine ? qh[fh] : 0u;
        float S1[4] = {0.f, 0.f, 0.f, 0.f}, S2[4] = {0.f, 0.f, 0.f, 0.f};
        mma16816(S1, ql[fa], qh[fa], ql[fb], qh[fb], kl[fa], kl[fb]); mma1688(S1, qm[h][0], qm[h][1], kl[fh]);
        mma16816(S2, ql[fa], qh[fa], ql[fb], qh[fb], kh[fa], kh[fb]); mma1688(S2, qm[h][0], qm[h][1], kh[fh]);
        sl[h][0] = S1[0]; sl[h][1] = S1[1];
        py[h] = softmax((sel0 ? S1[2] : S2[2]) * cy0, (sel1 ? S1[3] : S2[3]) * cy1, ky0, ky1);
    }
    TS(11);
    if (w == 0 && blk > 0) {
        ll_check5(hv, hp, ob);
#pragma unroll
        for (int f = 2; f < 4; f++) hv[f] = make_uint4(movm_t(hv[f].x), movm_t(hv[f].y), movm_t(hv[f].z), movm_t(hv[f].w));
        hv[4].x = movm_t(hv[4].x); hv[4].y = movm_t(hv[4].y);
    }
    const uint32_t kp[10] = {hv[0].x, hv[0].y, hv[4].z, hv[0].z, hv[0].w, hv[1].x, hv[1].y, hv[4].w, hv[1].z, hv[1].w};
    const uint32_t vp[10] = {hv[2].x, hv[2].y, hv[2].z, hv[2].w, hv[3].x, hv[3].y, hv[3].z, hv[3].w, hv[4].x, hv[4].y};
    TS(12);
    const uint4 ko[2] = {ldg_tab(16, tid & 127), ldg_tab(17, tid & 127)};
    const float bx0 = first && sel0 ? -INFINITY : 0.f, bx1 = first && sel1 ? -INFINITY : 0.f;
    float oacc[10][4];
#pragma unroll
    for (int h = 0; h < 4; h++) {
        const int fa = FA(h), fb = fa + 1, fh = FH(h);
        const bool mine = (h & 1) ? (q >= 2) : (q < 2);
        float S0[4] = {0.f, 0.f, 0.f, 0.f};
        mma16816(S0, ql[fa], qh[fa], ql[fb], qh[fb], kp[fa], kp[fb]); mma1688(S0, qm[h][0], qm[h][1], kp[fh]);
        const uint32_t px = softmax(fmaf(sel0 ? S0[0] : sl[h][0], cx0, bx0), fmaf(sel1 ? S0[1] : sl[h][1], cx1, bx1), kx0, kx1);
#pragma unroll
        for (int i = 0; i < 3; i++) {
            const int f = (i == 0) ? fa : (i == 1) ? fb : fh;
            float O[4] = {0.f, 0.f, 0.f, 0.f};
            mma16816(O, px & ~pm, py[h] & pm, 0u, py[h] & ~pm, vt[f][0], vt[f][1]);
            mma1688(O, px & pm, 0u, vp[f]);
            if (i < 2 || !(h & 1) || mine) { oacc[f][0] = O[0]; oacc[f][1] = O[1]; oacc[f][2] = O[2]; oacc[f][3] = O[3]; }
        }
    }
    TS(13);
    float aw[40];
    uint4 of[5];
    {
        const uint32_t fb = EPOCH ^ ob, mk[2] = {q == ((2 * w) & 3), q == ((2 * w + 1) & 3)};
        uint32_t* dst = &g_of[hg][blk][640 * wg + 16 * w].x + lane;
#pragma unroll
        for (int i = 0; i < 20; i++) {
            const uint32_t v = (pack2(oacc[i >> 1][2 * (i & 1)], oacc[i >> 1][2 * (i & 1) + 1]) & ~mk[i & 1]) | (fb & mk[i & 1]);
            u4r(of[i >> 2], i & 3) = v;
            asm volatile("st.relaxed.gpu.global.u32 [%0], %1;" ::"l"(dst + 256 * (i >> 1) + 32 * (i & 1)), "r"(v) : "memory");
        }
        if (lane == 0) mbar_arrive(BAR(att) + 8 * wg);
        TS(14);
    }
    const uint32_t obar = MISC(ob) + 32 * wg;
    named_bar(1 + wg, 128);
    kernel_stage<2>(ko, sb + Q_KDUMP + 2 * wg * KG_RES, MISC(kg), 2 * wg, sb + F_EO + wg * 8192, w, lane);
    TS(15);
    uint32_t res[20];
    mbar_wait(BAR(res), 0);
    const uint32_t ta = (8 * (mi >> 1) + mj) * 128 + (((2 * w + (mi & 1)) ^ mj) << 4);
    if (layer == 0) {
        const int tok = 16 * w + 8 * (mi & 1) + mj;
#pragma unroll
        for (int k = 0; k < 4; k++)
            ldsm_x4(res[4 * k], res[4 * k + 1], res[4 * k + 2], res[4 * k + 3], sb + W_RES + wg * 10240 + tok * 128 + (((2 * k + (mi >> 1)) ^ mj) << 4));
        ldsm_x4(res[16], res[17], res[18], res[19], sb + W_RES + wg * 10240 + 8192 + tok * 32 + (((mi >> 1) ^ (mj >> 2)) << 4));
    } else {
#pragma unroll
        for (int k = 0; k < 5; k++) ldsm_x4_t(res[4 * k], res[4 * k + 1], res[4 * k + 2], res[4 * k + 3], sb + W_RES + wg * 10240 + k * 2048 + ta);
    }
    fence_async_smem();
    __syncwarp();
    if (lane == 0) mbar_arrive(obar + 128 + 24);
    {
#pragma unroll
        for (int i = 0; i < 20; i++) { aw[2 * i] = bf_lo(res[i]); aw[2 * i + 1] = bf_hi(res[i]); }
        mbar_wait(BAR(wfull), 0);
        const uint64_t dm = mkdesc(sb + w_grp(0), 1280, 128, 0);
        wg_fence();
#pragma unroll
        for (int k = 0; k < 5; k++) wgmma_rs80(aw, of[k], dm + k * 160, 1);
        wg_commit();
    }
    conv_tables();
    wg_wait<0>();
    TS(8);
#pragma unroll 1
    for (int j = 1; j < 8; j++) {
        const int s = (j - 1) & 3;
        const uint64_t da = mkdesc(sb + o_slot(wg, s), 1024, 128, 0), dm = mkdesc(sb + w_grp(j), 1280, 128, 0);
        if (s == 2) mbar_wait(BAR(wfull) + 2 * (j + 1), 0);
        mbar_wait(obar + 64 + 8 * s, s == 3 ? layer : j > 4);
        if (j == 1) TS(17);
        if (j == 5) TS(18);
        wg_fence();
#pragma unroll
        for (int k = 0; k < 5; k++) wgmma_ss80(aw, da + k * 128, dm + k * 160);
        wg_commit();
        wg_wait<1>();
        if (j > 1 && j < 5 && lane == 0) mbar_arrive(obar + 128 + 8 * (j - 2));
    }
    if (lane == 0) mbar_arrive(BAR(soon) + 8 * wg);
    named_bar(1 + wg, 128);
    wg_wait<0>();
    TS(19);
    {
        float a[2][4] = {{0.f, 0.f, 0.f, 0.f}, {0.f, 0.f, 0.f, 0.f}};
#pragma unroll
        for (int i = 0; i < 40; i++) { a[i & 1][i & 2] += aw[i]; a[i & 1][(i & 2) + 1] = fmaf(aw[i], aw[i], a[i & 1][(i & 2) + 1]); }
#pragma unroll
        for (int j = 0; j < 4; j++) { a[0][j] += a[1][j]; a[0][j] += __shfl_xor_sync(~0u, a[0][j], 1); a[0][j] += __shfl_xor_sync(~0u, a[0][j], 2); }
        if (q == 0) st_ll4(&g_sp2[blk][warp][hg][g], (__float_as_uint(a[0][0]) & ~1u) | ob, __float_as_uint(a[0][1]), __float_as_uint(a[0][2]), __float_as_uint(a[0][3]));
    }
    TS(23);
#pragma unroll
    for (int i = 0; i < 20; i++) res[i] = pack2(aw[2 * i], aw[2 * i + 1]);
    {
        const uint32_t mk = (g & 3) ? 0u : 0x00010001u;
#pragma unroll
        for (int k = 0; k < 5; k++) {
            uint32_t m[4];
#pragma unroll
            for (int i = 0; i < 4; i++) m[i] = (res[4 * k + i] & ~mk) | (mk & (0u - ob));
            stsm_x4_t(sb + w_out(wg) + k * 2048 + ta, m[0], m[1], m[2], m[3]);
        }
        fence_async_smem();
        named_bar(1 + wg, 128);
        if (w == 0 && elect_one()) {
            asm volatile("cp.async.bulk.tensor.2d.global.shared::cta.bulk_group [%0, {%2, %3}], [%1];"
                         ::"l"(TMAP(7)), "r"(sb + w_out(wg)), "r"(1024 * wg + 64 * blk), "r"(hg * 80) : "memory");
            bulk_commit();
            mbar_arrive(BAR(staged));
        }
        __syncwarp();
        TS(20);
    }
    if (layer) {
#pragma unroll
        for (int k = 0; k < 5; k++) stsm_x4_t(sb + W_RES + wg * 10240 + k * 2048 + ta, res[4 * k], res[4 * k + 1], res[4 * k + 2], res[4 * k + 3]);
    }
    TS(22);
    TS_PHASE(2 * layer + 1);
    TS(0);
    indices();
    conv_wg<2>(cta_channel(bx, 2 * (warp >> 2)), layer, sb + F_EO + (warp >> 2) * 8192, sb + (1 + 2 * (warp >> 2)) * Q_SB, sb + F_S23, MISC(kg.kexp) + 8 * (warp >> 2),
               MISC(epoch), sb, BAR(st), BAR(fdone0), warp, lane, fa1, ftw, [&] {
        if ((warp & 3) == 0 && elect_one()) {
            asm volatile("cp.async.bulk.wait_group.read 0;" ::: "memory");
            if (layer == 0) { mbar_arrive_cta(BAR(wfree), 0); mbar_arrive_cta(BAR(wfree), 1); }
        }
        __syncwarp();
        if (warp < 4) mbar_wait(BAR(staged), 0);
    }, [&] {
        if (layer == 0 && warp >= 4 && elect_one()) {
            mbar_wait(BAR(wfree), 0);
            issue_w(BAR(full) + sizeof(Bars), warp - 4, 1);
        }
        __syncwarp();
    } TS_PASS);
    __syncwarp();
    if (lane == 0) mbar_arrive(warp < 4 ? BAR(fdone0) : BAR(fdone1));
    TS(20);
    asm volatile("setmaxnreg.dec.sync.aligned.u32 168;");
    }
    named_bar(1 + (warp >> 2), 128);
    asm volatile("setmaxnreg.dec.sync.aligned.u32 %0;" ::"n"(504 - 2 * R_CONS));
    }
    indices();
    const int cq = 4 * (warp >> 1) + (lane & 3), tg = 8 * (warp & 1) + (lane >> 2);
    const uint32_t fb = ~EPOCH & 1u;
    uint2 xr[4][2];
    __syncthreads();
    if (tid < 320) {
#pragma unroll
        for (int i = 0; i < 8; i++) {
            const int ch = 4 * cq + (i >> 1);
            asm volatile("ld.shared.v2.u32 {%0, %1}, [%2];" : "=r"(xr[i >> 1][i & 1].x), "=r"(xr[i >> 1][i & 1].y)
                         : "r"(sb + W_RES + (i & 1) * 10240 + ch * 128 + (((tg >> 1) ^ (ch & 7)) << 4) + (tg & 1) * 8) : "memory");
        }
    }
    if (tid < 320) {
        const uint4* src = &g_of[hg][blk][64 * cq + tg];
        uint4 v[4];
#pragma unroll
        for (int i = 0; i < 4; i++) v[i] = make_uint4(~fb, ~fb, ~fb, ~fb);
        auto miss = [&](int i) { return (((warp & 1) ? u4(v[i], 2 * (i & 1) + 1) : u4(v[i], 2 * (i & 1))) ^ fb) & 1u; };
        int spin = 0;
        while (true) {
#pragma unroll
            for (int i = 0; i < 4; i++) if (miss(i)) v[i] = ld_ll4(src + 16 * i);
            if (!(miss(0) | miss(1) | miss(2) | miss(3)) || ++spin >= (1 << 18)) break;
        }
        TS(21);
#pragma unroll
        for (int i = 0; i < 16; i++) asm("add.rn.bf16x2 %0, %0, %1;" : "+r"(u4r(v[i >> 2], i & 3)) : "r"((i & 1) ? xr[i >> 2][(i >> 1) & 1].y : xr[i >> 2][(i >> 1) & 1].x));
#pragma unroll
        for (int j = 0; j < 8; j++) {
            const uint32_t sel = (j & 2) ? 0x7632 : 0x5410;
            const int k = 2 * (j & 1) + (j >> 2);
            asm volatile("st.shared.v2.u32 [%0], {%1, %2};" ::"r"(sb + 2 * Q_SB + (16 * j + tg) * 160 + cq * 8),
                         "r"(__byte_perm(u4(v[0], k), u4(v[1], k), sel)), "r"(__byte_perm(u4(v[2], k), u4(v[3], k), sel)) : "memory");
        }
        fence_async_smem();
    }
    __syncthreads();
    if (warp == 0 && elect_one()) {
        asm volatile("cp.async.bulk.tensor.3d.global.shared::cta.bulk_group [%0, {%2, %3, 0}], [%1];" ::"l"(TMAP(9)), "r"(sb + 2 * Q_SB), "r"(80 * hg), "r"(16 * blk) : "memory");
        bulk_commit();
        asm volatile("cp.async.bulk.wait_group.read 0;" ::: "memory");
    }
    if (bx == 0 && tid == 0) g_epoch = (EPOCH + 1) & 0x3FFFFFFFu;
    TS(22);
    TS_END;
}
typedef CUresult (*EncodeTiledFn)(CUtensorMap*, CUtensorMapDataType, cuuint32_t, void*, const cuuint64_t*, const cuuint64_t*, const cuuint32_t*,
                                  const cuuint32_t*, CUtensorMapInterleave, CUtensorMapSwizzle, CUtensorMapL2promotion, CUtensorMapFloatOOBfill);

static void make_map(EncodeTiledFn enc, CUtensorMap* m, const void* base, int rank, const cuuint64_t* dims, const cuuint64_t* strides,
                     const cuuint32_t* box, CUtensorMapSwizzle sw) {
    cuuint32_t es[4] = {1, 1, 1, 1};
    enc(m, CU_TENSOR_MAP_DATA_TYPE_BFLOAT16, rank, (void*)base, dims, strides, box, es, CU_TENSOR_MAP_INTERLEAVE_NONE, sw,
        sw == CU_TENSOR_MAP_SWIZZLE_128B ? CU_TENSOR_MAP_L2_PROMOTION_L2_128B : CU_TENSOR_MAP_L2_PROMOTION_NONE, CU_TENSOR_MAP_FLOAT_OOB_FILL_NONE);
}

template <typename... KArgs, typename... Args>
static void launch(void (*kern)(KArgs...), int grid, int block, int smem, int cluster, bool pdl, Args... args) {
    cudaLaunchConfig_t cfg = {};
    cfg.gridDim = dim3(grid); cfg.blockDim = dim3(block); cfg.dynamicSmemBytes = smem; cfg.stream = cudaStreamPerThread;
    cudaLaunchAttribute at[2];
    int n = 0;
    if (cluster > 1) { at[n].id = cudaLaunchAttributeClusterDimension; at[n].val.clusterDim.x = cluster; at[n].val.clusterDim.y = 1; at[n].val.clusterDim.z = 1; n++; }
    if (pdl) { at[n].id = cudaLaunchAttributeProgrammaticStreamSerialization; at[n].val.programmaticStreamSerializationAllowed = 1; n++; }
    cfg.attrs = at; cfg.numAttrs = n;
    cudaLaunchKernelEx(&cfg, kern, KArgs(args)...);
}

struct HostState {
    bool ready = false;
    const void* key[4] = {nullptr, nullptr, nullptr, nullptr};
    CUtensorMap mX[2], mRes[2], mW, mWr, mWo, mOut, mFin, mResA;
    bf16 *x1T, *x2T;
    unsigned* epoch;
};

extern "C" void kernel_launch(void* const* d_in, const int* in_sizes, int n_in, void* d_out, int out_size) {
    const bf16* x = (const bf16*)d_in[0];
    const bf16* wqkv = (const bf16*)d_in[1];
    const bf16* wo = (const bf16*)d_in[2];
    const bf16* lar = (const bf16*)d_in[4];
    const bf16* aim = (const bf16*)d_in[5];
    const bf16* cre = (const bf16*)d_in[6];
    const bf16* cim = (const bf16*)d_in[7];
    const bf16* logdt = (const bf16*)d_in[8];
    const bf16* dskip = (const bf16*)d_in[9];
    static HostState hs;
    if (!hs.ready || hs.key[0] != wqkv || hs.key[1] != wo || hs.key[2] != x || hs.key[3] != d_out) {
        void* fn = nullptr;
        cudaDriverEntryPointQueryResult qr;
        cudaGetDriverEntryPoint("cuTensorMapEncodeTiled", &fn, cudaEnableDefault, &qr);
        EncodeTiledFn enc = (EncodeTiledFn)fn;
        cudaGetSymbolAddress((void**)&hs.epoch, g_epoch);
        cudaGetSymbolAddress((void**)&hs.x1T, g_x1T);
        cudaGetSymbolAddress((void**)&hs.x2T, g_x2T);
        {
            cuuint64_t d[3] = {DM, SEQ / 2, 2}, s[2] = {DM * 4, DM * 2};
            cuuint32_t b[3] = {64, 64, 2}, ba[3] = {64, 64, 1}, br[3] = {16, 64, 1};
            make_map(enc, &hs.mX[0], x, 3, d, s, b, CU_TENSOR_MAP_SWIZZLE_128B);
            make_map(enc, &hs.mResA, x, 3, d, s, ba, CU_TENSOR_MAP_SWIZZLE_128B);
            make_map(enc, &hs.mRes[0], x, 3, d, s, br, CU_TENSOR_MAP_SWIZZLE_32B);
            cuuint64_t d2[3] = {SEQ / 2, DM, 2}, s2[2] = {XP * 2, SEQ};
            cuuint32_t b2[3] = {64, 80, 2};
            make_map(enc, &hs.mX[1], hs.x2T, 3, d2, s2, b, CU_TENSOR_MAP_SWIZZLE_128B);
            make_map(enc, &hs.mRes[1], hs.x2T, 3, d2, s2, b2, CU_TENSOR_MAP_SWIZZLE_128B);
            cuuint64_t d3[2] = {SEQ, DM};
            make_map(enc, &hs.mOut, hs.x1T, 2, d3, s2, b2, CU_TENSOR_MAP_SWIZZLE_128B);
        }
        { cuuint64_t d[2] = {3 * DM, DM}, s[1] = {3 * DM * 2}; cuuint32_t b[2] = {64, 32};
          make_map(enc, &hs.mW, wqkv, 2, d, s, b, CU_TENSOR_MAP_SWIZZLE_128B); }
        { cuuint64_t d[3] = {DM, DM, 3}, s[2] = {3 * DM * 2, DM * 2}; cuuint32_t b[3] = {16, 32, 3};
          make_map(enc, &hs.mWr, wqkv, 3, d, s, b, CU_TENSOR_MAP_SWIZZLE_32B); }
        { cuuint64_t d[4] = {8, 8, DM / 8, DM / 8}, s[3] = {DM * 2, 16, DM * 16}; cuuint32_t b[4] = {8, 8, 10, 5};
          make_map(enc, &hs.mWo, wo, 4, d, s, b, CU_TENSOR_MAP_SWIZZLE_NONE); }
        { cuuint64_t d[3] = {DM, SEQ / 8, 8}, s[2] = {DM * 16, DM * 2}; cuuint32_t b[3] = {80, 16, 8};
          make_map(enc, &hs.mFin, d_out, 3, d, s, b, CU_TENSOR_MAP_SWIZZLE_NONE); }
        cudaFuncSetAttribute(fused_kernel, cudaFuncAttributeMaxDynamicSharedMemorySize, Q_SMEM);
        hs.key[0] = wqkv; hs.key[1] = wo; hs.key[2] = x; hs.key[3] = d_out;
        hs.ready = true;
    }
    const SsmParams sp = {lar, aim, cre, cim, logdt, dskip, hs.epoch};
    launch(fused_kernel, 128, 384, Q_SMEM, 2, false, sp, hs.mX[0], hs.mX[1], hs.mW, hs.mWr, hs.mRes[0], hs.mRes[1], hs.mOut, hs.mWo, hs.mFin, hs.mResA);
}
```

```cpp
#include <cuda_runtime.h>
#include <cuda.h>
#include <cuda_bf16.h>
#include <cuda_fp16.h>
#include <stdint.h>

typedef __nv_bfloat16 bf16;

constexpr int SEQ = 2048;
constexpr int DM  = 640;
constexpr int XP  = SEQ + 64;
constexpr int NMODE = 192;
#define HINT_SPINS (1 << 18)

__device__ __forceinline__ uint32_t s2u(const void* p) { return (uint32_t)__cvta_generic_to_shared(p); }
__device__ __forceinline__ void mbar_init(uint32_t b, int c) { asm volatile("mbarrier.init.shared::cta.b64 [%0], %1;" ::"r"(b), "r"(c)); }
__device__ __forceinline__ void mbar_expect(uint32_t b, uint32_t bytes) { asm volatile("mbarrier.arrive.expect_tx.shared::cta.b64 _, [%0], %1;" ::"r"(b), "r"(bytes) : "memory"); }
__device__ __forceinline__ void mbar_arrive(uint32_t b) { asm volatile("mbarrier.arrive.shared::cta.b64 _, [%0];" ::"r"(b) : "memory"); }
__device__ __forceinline__ void mbar_arrive_cta(uint32_t b, uint32_t cta) {
    asm volatile("{\n.reg .b32 ra;\nmapa.shared::cluster.u32 ra, %0, %1;\nmbarrier.arrive.shared::cluster.b64 _, [ra];\n}" ::"r"(b), "r"(cta) : "memory");
}
__device__ __forceinline__ void mbar_wait(uint32_t b, uint32_t ph) {
#ifdef M_SAFE
    asm volatile("{\n.reg .pred p;\n.reg .u32 n;\nmbarrier.try_wait.parity.shared::cta.b64 p, [%0], %1;\n@p bra D;\nmov.u32 n, 0;\n"
                 "W: mbarrier.try_wait.parity.shared::cta.b64 p, [%0], %1;\n@p bra D;\nadd.u32 n, n, 1;\nsetp.lt.u32 p, n, 4194304;\n@p bra W;\ntrap;\nD:\n}"
                 ::"r"(b), "r"(ph) : "memory");
#else
    asm volatile("{\n.reg .pred p;\nW: mbarrier.try_wait.parity.shared::cta.b64 p, [%0], %1;\n@!p bra W;\n}" ::"r"(b), "r"(ph) : "memory");
#endif
}
__device__ __forceinline__ void fence_mbar_init() { asm volatile("fence.mbarrier_init.release.cluster;" ::: "memory"); }
__device__ __forceinline__ void cluster_sync() { asm volatile("barrier.cluster.arrive.aligned;\nbarrier.cluster.wait.aligned;" ::: "memory"); }
__device__ __forceinline__ void pdl_wait() { asm volatile("griddepcontrol.wait;" ::: "memory"); }
__device__ __forceinline__ void pdl_launch() { asm volatile("griddepcontrol.launch_dependents;" ::: "memory"); }
__device__ __forceinline__ void named_bar(int id, int n) { asm volatile("bar.sync %0, %1;" ::"r"(id), "r"(n) : "memory"); }
__device__ __forceinline__ void fence_async_smem() { asm volatile("fence.proxy.async.shared::cta;" ::: "memory"); }

__device__ __forceinline__ void tma2d(uint32_t dst, const CUtensorMap* m, int c0, int c1, uint32_t bar) {
    asm volatile("cp.async.bulk.tensor.2d.shared::cluster.global.mbarrier::complete_tx::bytes [%0], [%1, {%3, %4}], [%2];"
                 ::"r"(dst), "l"(m), "r"(bar), "r"(c0), "r"(c1) : "memory");
}
__device__ __forceinline__ void tma2d_mc(uint32_t dst, const CUtensorMap* m, int c0, int c1, uint32_t bar, uint16_t mask) {
    asm volatile("cp.async.bulk.tensor.2d.shared::cluster.global.mbarrier::complete_tx::bytes.multicast::cluster [%0], [%1, {%3, %4}], [%2], %5;"
                 ::"r"(dst), "l"(m), "r"(bar), "r"(c0), "r"(c1), "h"(mask) : "memory");
}
__device__ __forceinline__ void tma3d(uint32_t dst, const CUtensorMap* m, int c0, int c1, int c2, uint32_t bar) {
    asm volatile("cp.async.bulk.tensor.3d.shared::cluster.global.mbarrier::complete_tx::bytes [%0], [%1, {%3, %4, %5}], [%2];"
                 ::"r"(dst), "l"(m), "r"(bar), "r"(c0), "r"(c1), "r"(c2) : "memory");
}
__device__ __forceinline__ void tma3d_mc(uint32_t dst, const CUtensorMap* m, int c0, int c1, int c2, uint32_t bar, uint16_t mask) {
    asm volatile("cp.async.bulk.tensor.3d.shared::cluster.global.mbarrier::complete_tx::bytes.multicast::cluster [%0], [%1, {%3, %4, %5}], [%2], %6;"
                 ::"r"(dst), "l"(m), "r"(bar), "r"(c0), "r"(c1), "r"(c2), "h"(mask) : "memory");
}
__device__ __forceinline__ void bulk_g2s(uint32_t dst, const void* src, uint32_t bytes, uint32_t bar) {
    asm volatile("cp.async.bulk.shared::cluster.global.mbarrier::complete_tx::bytes [%0], [%1], %2, [%3];"
                 ::"r"(dst), "l"(src), "r"(bytes), "r"(bar) : "memory");
}
__device__ __forceinline__ void bulk_g2s_mc(uint32_t dst, const void* src, uint32_t bytes, uint32_t bar, uint16_t mask) {
    asm volatile("cp.async.bulk.shared::cluster.global.mbarrier::complete_tx::bytes.multicast::cluster [%0], [%1], %2, [%3], %4;"
                 ::"r"(dst), "l"(src), "r"(bytes), "r"(bar), "h"(mask) : "memory");
}
__device__ __forceinline__ void prefetch_l2(const void* p, uint32_t bytes) { asm volatile("cp.async.bulk.prefetch.L2.global [%0], %1;" ::"l"(p), "r"(bytes) : "memory"); }
__device__ __forceinline__ void prefetch_tmap(const CUtensorMap* m) { asm volatile("prefetch.tensormap [%0];" ::"l"(m) : "memory"); }

__device__ __forceinline__ void wg_fence() { asm volatile("wgmma.fence.sync.aligned;" ::: "memory"); }
__device__ __forceinline__ void wg_commit() { asm volatile("wgmma.commit_group.sync.aligned;" ::: "memory"); }
template <int N> __device__ __forceinline__ void wg_wait() { asm volatile("wgmma.wait_group.sync.aligned %0;" ::"n"(N) : "memory"); }
__device__ __forceinline__ uint64_t mkdesc(uint32_t addr, uint32_t lbo, uint32_t sbo, uint32_t mode) {
    return (uint64_t)((addr & 0x3FFFF) >> 4) | ((uint64_t)(lbo >> 4) << 16) | ((uint64_t)(sbo >> 4) << 32) | ((uint64_t)mode << 62);
}

__device__ __forceinline__ void mma16816(float (&c)[4], uint32_t a0, uint32_t a1, uint32_t a2, uint32_t a3, uint32_t b0, uint32_t b1) {
    asm("mma.sync.aligned.m16n8k16.row.col.f32.bf16.bf16.f32 {%0,%1,%2,%3},{%4,%5,%6,%7},{%8,%9},{%0,%1,%2,%3};"
                 : "+f"(c[0]), "+f"(c[1]), "+f"(c[2]), "+f"(c[3]) : "r"(a0), "r"(a1), "r"(a2), "r"(a3), "r"(b0), "r"(b1));
}
__device__ __forceinline__ void mma1688(float (&c)[4], uint32_t a0, uint32_t a1, uint32_t b0) {
    asm("mma.sync.aligned.m16n8k8.row.col.f32.bf16.bf16.f32 {%0,%1,%2,%3},{%4,%5},{%6},{%0,%1,%2,%3};"
                 : "+f"(c[0]), "+f"(c[1]), "+f"(c[2]), "+f"(c[3]) : "r"(a0), "r"(a1), "r"(b0));
}
__device__ __forceinline__ void ldsm_x4(uint32_t& r0, uint32_t& r1, uint32_t& r2, uint32_t& r3, uint32_t a) {
    asm volatile("ldmatrix.sync.aligned.m8n8.x4.shared.b16 {%0,%1,%2,%3}, [%4];" : "=r"(r0), "=r"(r1), "=r"(r2), "=r"(r3) : "r"(a) : "memory");
}
__device__ __forceinline__ void ldsm_x4_t(uint32_t& r0, uint32_t& r1, uint32_t& r2, uint32_t& r3, uint32_t a) {
    asm volatile("ldmatrix.sync.aligned.m8n8.x4.trans.shared.b16 {%0,%1,%2,%3}, [%4];" : "=r"(r0), "=r"(r1), "=r"(r2), "=r"(r3) : "r"(a) : "memory");
}
__device__ __forceinline__ void ldsm_x2(uint32_t& r0, uint32_t& r1, uint32_t a) {
    asm volatile("ldmatrix.sync.aligned.m8n8.x2.shared.b16 {%0,%1}, [%2];" : "=r"(r0), "=r"(r1) : "r"(a) : "memory");
}
__device__ __forceinline__ void ldsm_x2_t(uint32_t& r0, uint32_t& r1, uint32_t a) {
    asm volatile("ldmatrix.sync.aligned.m8n8.x2.trans.shared.b16 {%0,%1}, [%2];" : "=r"(r0), "=r"(r1) : "r"(a) : "memory");
}
__device__ __forceinline__ void stsm_x4(uint32_t a, uint32_t r0, uint32_t r1, uint32_t r2, uint32_t r3) {
    asm volatile("stmatrix.sync.aligned.m8n8.x4.shared.b16 [%0], {%1,%2,%3,%4};" ::"r"(a), "r"(r0), "r"(r1), "r"(r2), "r"(r3) : "memory");
}
__device__ __forceinline__ void stsm_x4_t(uint32_t a, uint32_t r0, uint32_t r1, uint32_t r2, uint32_t r3) {
    asm volatile("stmatrix.sync.aligned.m8n8.x4.trans.shared.b16 [%0], {%1,%2,%3,%4};" ::"r"(a), "r"(r0), "r"(r1), "r"(r2), "r"(r3) : "memory");
}
__device__ __forceinline__ void stsm_x2(uint32_t a, uint32_t r0, uint32_t r1) {
    asm volatile("stmatrix.sync.aligned.m8n8.x2.shared.b16 [%0], {%1,%2};" ::"r"(a), "r"(r0), "r"(r1) : "memory");
}
__device__ __forceinline__ uint32_t movm_t(uint32_t a) {
    uint32_t d;
    asm volatile("movmatrix.sync.aligned.m8n8.trans.b16 %0, %1;" : "=r"(d) : "r"(a));
    return d;
}
__device__ __forceinline__ uint32_t lds32(uint32_t a) { uint32_t v; asm volatile("ld.shared.u32 %0, [%1];" : "=r"(v) : "r"(a) : "memory"); return v; }
__device__ __forceinline__ uint32_t ldsv32(uint32_t a) { uint32_t v; asm volatile("ld.volatile.shared.u32 %0, [%1];" : "=r"(v) : "r"(a) : "memory"); return v; }
__device__ __forceinline__ void sts32(uint32_t a, uint32_t v) { asm volatile("st.shared.u32 [%0], %1;" ::"r"(a), "r"(v) : "memory"); }
__device__ __forceinline__ uint4 lds128(uint32_t a) { uint4 v; asm volatile("ld.shared.v4.u32 {%0,%1,%2,%3}, [%4];" : "=r"(v.x), "=r"(v.y), "=r"(v.z), "=r"(v.w) : "r"(a) : "memory"); return v; }
__device__ __forceinline__ void sts128(uint32_t a, uint4 v) { asm volatile("st.shared.v4.u32 [%0], {%1,%2,%3,%4};" ::"r"(a), "r"(v.x), "r"(v.y), "r"(v.z), "r"(v.w) : "memory"); }

__device__ __forceinline__ void stg128(void* p, uint4 v) { asm volatile("st.global.v4.u32 [%0], {%1,%2,%3,%4};" ::"l"(p), "r"(v.x), "r"(v.y), "r"(v.z), "r"(v.w) : "memory"); }

__device__ __forceinline__ uint4 ldg128(const void* p) { uint4 v; asm volatile("ld.global.v4.u32 {%0,%1,%2,%3}, [%4];" : "=r"(v.x), "=r"(v.y), "=r"(v.z), "=r"(v.w) : "l"(p) : "memory"); return v; }
__device__ __forceinline__ uint2 ldg64(const void* p) { uint2 v; asm volatile("ld.global.v2.u32 {%0,%1}, [%2];" : "=r"(v.x), "=r"(v.y) : "l"(p) : "memory"); return v; }
__device__ __forceinline__ uint32_t ldg32(const void* p) { uint32_t v; asm volatile("ld.global.u32 %0, [%1];" : "=r"(v) : "l"(p) : "memory"); return v; }

__device__ __forceinline__ uint32_t pack2(float lo, float hi) {
    uint32_t r;
    asm("cvt.rn.bf16x2.f32 %0, %1, %2;" : "=r"(r) : "f"(hi), "f"(lo));
    return r;
}
__device__ __forceinline__ float bf_lo(uint32_t v) { return __uint_as_float(v << 16); }
__device__ __forceinline__ float bf_hi(uint32_t v) { return __uint_as_float(v & 0xFFFF0000u); }
__device__ __forceinline__ float rbf(float x) { return __uint_as_float(pack2(0.f, x) & 0xFFFF0000u); }
__device__ __forceinline__ float ex2(float x) { float r; asm("ex2.approx.ftz.f32 %0, %1;" : "=f"(r) : "f"(x)); return r; }

__device__ __forceinline__ float2 ln_finish(float sum, float sumsq) {
    const float m = sum * (1.0f / DM);
    const float v = fmaxf(fmaf(sumsq, 1.0f / DM, -m * m), 0.f);
    float s, r;
    asm("sqrt.approx.ftz.f32 %0, %1;" : "=f"(s) : "f"(rbf(rbf(v) + 1e-5f)));
    asm("rcp.approx.ftz.f32 %0, %1;" : "=f"(r) : "f"(rbf(s)));
    return make_float2(m, r);
}
__device__ __forceinline__ uint32_t ln_finish_packed(float sum, float sumsq) {
    const float m = sum * (1.0f / DM);
    const float v = fmaxf(fmaf(sumsq, 1.0f / DM, -m * m), 0.f);
    float s;
    asm("sqrt.approx.ftz.f32 %0, %1;" : "=f"(s) : "f"(rbf(rbf(v) + 1e-5f)));
    return pack2(s, m);
}
__device__ __forceinline__ float frsq(float x) { float r; asm("rsqrt.approx.ftz.f32 %0, %1;" : "=f"(r) : "f"(x)); return r; }
__device__ __forceinline__ float frcp(float x) { float r; asm("rcp.approx.ftz.f32 %0, %1;" : "=f"(r) : "f"(x)); return r; }
__device__ __forceinline__ bool elect_one() {
    uint32_t p;
    asm volatile("{\n.reg .pred p;\nelect.sync _|p, 0xffffffff;\nselp.u32 %0, 1, 0, p;\n}" : "=r"(p));
    return p != 0;
}
__device__ __forceinline__ void cluster_arrive_relaxed() { asm volatile("barrier.cluster.arrive.relaxed.aligned;" ::: "memory"); }
__device__ __forceinline__ void cluster_wait() { asm volatile("barrier.cluster.wait.aligned;" ::: "memory"); }
__device__ __forceinline__ uint32_t miss(uint32_t acc, uint32_t v, uint32_t mark) {
    uint32_t r;
    asm("lop3.b32 %0, %1, %2, %3, 0xF6;" : "=r"(r) : "r"(acc), "r"(v), "r"(mark));
    return r;
}
__device__ __forceinline__ unsigned long long ld_ll(const unsigned long long* p) {
    unsigned long long v;
    asm volatile("ld.relaxed.gpu.global.b64 %0, [%1];" : "=l"(v) : "l"(p) : "memory");
    return v;
}
__device__ __forceinline__ void st_ll(unsigned long long* p, uint32_t payload, uint32_t tag) {
    const unsigned long long v = (unsigned long long)payload | ((unsigned long long)tag << 32);
    asm volatile("st.relaxed.gpu.global.b64 [%0], %1;" ::"l"(p), "l"(v) : "memory");
}
__device__ __forceinline__ uint4 ld_ll4(const uint4* p) {
    uint4 v;
    asm volatile("{\n.reg .b128 t;\n.reg .b64 a, b;\nld.relaxed.gpu.global.b128 t, [%4];\nmov.b128 {a, b}, t;\nmov.b64 {%0, %1}, a;\nmov.b64 {%2, %3}, b;\n}"
                 : "=r"(v.x), "=r"(v.y), "=r"(v.z), "=r"(v.w) : "l"(p) : "memory");
    return v;
}
__device__ __forceinline__ void st_ll4(uint4* p, uint32_t x, uint32_t y, uint32_t z, uint32_t w) {
    asm volatile("{\n.reg .b128 t;\n.reg .b64 a, b;\nmov.b64 a, {%1, %2};\nmov.b64 b, {%3, %4};\nmov.b128 t, {a, b};\nst.relaxed.gpu.global.b128 [%0], t;\n}"
                 ::"l"(p), "r"(x), "r"(y), "r"(z), "r"(w) : "memory");
}

__device__ __forceinline__ void bulk_s2g(void* dst, uint32_t src, uint32_t bytes) {
    asm volatile("cp.async.bulk.global.shared::cta.bulk_group [%0], [%1], %2;" ::"l"(dst), "r"(src), "r"(bytes) : "memory");
}
__device__ __forceinline__ void bulk_commit() { asm volatile("cp.async.bulk.commit_group;" ::: "memory"); }
__device__ __forceinline__ void bulk_wait() { asm volatile("cp.async.bulk.wait_group 0;" ::: "memory"); }
__device__ __forceinline__ void fence_async_global() { asm volatile("fence.proxy.async.global;" ::: "memory"); }
__device__ __forceinline__ void fence_release() { asm volatile("fence.release.gpu;" ::: "memory"); }
__device__ __forceinline__ void fence_acquire() { asm volatile("fence.acquire.gpu;" ::: "memory"); }
__device__ __forceinline__ void ll_check5(uint4 (&f)[5], const uint4* p, uint32_t mark) {
#define LL_LD(i, a, b, c, d) "ld.relaxed.gpu.global.b128 q, [%20 + " #i "];\nmov.b128 {u, v}, q;\nmov.b64 {%" #a ", %" #b "}, u;\nmov.b64 {%" #c ", %" #d "}, v;\n"
    asm volatile("{\n.reg .pred p;\n.reg .b32 t, n, m;\n.reg .b128 q;\n.reg .b64 u, v;\nmov.u32 n, 0x7FFFF;\n"
                 "L:\nlop3.b32 t, %0, %4, %21, 0x7E;\nlop3.b32 t, t, %8, %21, 0xF6;\nlop3.b32 t, t, %12, %21, 0xF6;\nlop3.b32 t, t, %16, %21, 0xF6;\n"
                 "shr.u32 m, n, 18;\nand.b32 t, t, m;\nsetp.ne.u32 p, t, 0;\nvote.sync.any.pred p, p, 0xffffffff;\n@!p bra.uni D;\n"
                 LL_LD(0, 0, 1, 2, 3) LL_LD(512, 4, 5, 6, 7) LL_LD(1024, 8, 9, 10, 11) LL_LD(1536, 12, 13, 14, 15) LL_LD(2048, 16, 17, 18, 19)
                 "sub.u32 n, n, 1;\nbra.uni L;\nD:\n}"
                 : "+r"(f[0].x), "+r"(f[0].y), "+r"(f[0].z), "+r"(f[0].w), "+r"(f[1].x), "+r"(f[1].y), "+r"(f[1].z), "+r"(f[1].w), "+r"(f[2].x), "+r"(f[2].y),
                   "+r"(f[2].z), "+r"(f[2].w), "+r"(f[3].x), "+r"(f[3].y), "+r"(f[3].z), "+r"(f[3].w), "+r"(f[4].x), "+r"(f[4].y), "+r"(f[4].z), "+r"(f[4].w)
                 : "l"(p), "r"(mark) : "memory");
}
template<int TA, int TB>
__device__ __forceinline__ void wgmma_n192(float (&d)[96], uint64_t da, uint64_t db, int scale_d) {
  asm volatile("{\n.reg .pred p;\nsetp.ne.b32 p, %98, 0;\n"
    "wgmma.mma_async.sync.aligned.m64n192k16.f32.bf16.bf16 "
    "{%0, %1, %2, %3, %4, %5, %6, %7, %8, %9, %10, %11, %12, %13, %14, %15, %16, %17, %18, %19, %20, %21, %22, %23, %24, %25, %26, %27, %28, %29, %30, %31, %32, %33, %34, %35, %36, %37, %38, %39, %40, %41, %42, %43, %44, %45, %46, %47, %48, %49, %50, %51, %52, %53, %54, %55, %56, %57, %58, %59, %60, %61, %62, %63, %64, %65, %66, %67, %68, %69, %70, %71, %72, %73, %74, %75, %76, %77, %78, %79, %80, %81, %82, %83, %84, %85, %86, %87, %88, %89, %90, %91, %92, %93, %94, %95}, %96, %97, p, 1, 1, %99, %100;\n}\n"
    : "+f"(d[0]), "+f"(d[1]), "+f"(d[2]), "+f"(d[3]), "+f"(d[4]), "+f"(d[5]), "+f"(d[6]), "+f"(d[7]), "+f"(d[8]), "+f"(d[9]), "+f"(d[10]), "+f"(d[11]), "+f"(d[12]), "+f"(d[13]), "+f"(d[14]), "+f"(d[15]), "+f"(d[16]), "+f"(d[17]), "+f"(d[18]), "+f"(d[19]), "+f"(d[20]), "+f"(d[21]), "+f"(d[22]), "+f"(d[23]), "+f"(d[24]), "+f"(d[25]), "+f"(d[26]), "+f"(d[27]), "+f"(d[28]), "+f"(d[29]), "+f"(d[30]), "+f"(d[31]), "+f"(d[32]), "+f"(d[33]), "+f"(d[34]), "+f"(d[35]), "+f"(d[36]), "+f"(d[37]), "+f"(d[38]), "+f"(d[39]), "+f"(d[40]), "+f"(d[41]), "+f"(d[42]), "+f"(d[43]), "+f"(d[44]), "+f"(d[45]), "+f"(d[46]), "+f"(d[47]), "+f"(d[48]), "+f"(d[49]), "+f"(d[50]), "+f"(d[51]), "+f"(d[52]), "+f"(d[53]), "+f"(d[54]), "+f"(d[55]), "+f"(d[56]), "+f"(d[57]), "+f"(d[58]), "+f"(d[59]), "+f"(d[60]), "+f"(d[61]), "+f"(d[62]), "+f"(d[63]), "+f"(d[64]), "+f"(d[65]), "+f"(d[66]), "+f"(d[67]), "+f"(d[68]), "+f"(d[69]), "+f"(d[70]), "+f"(d[71]), "+f"(d[72]), "+f"(d[73]), "+f"(d[74]), "+f"(d[75]), "+f"(d[76]), "+f"(d[77]), "+f"(d[78]), "+f"(d[79]), "+f"(d[80]), "+f"(d[81]), "+f"(d[82]), "+f"(d[83]), "+f"(d[84]), "+f"(d[85]), "+f"(d[86]), "+f"(d[87]), "+f"(d[88]), "+f"(d[89]), "+f"(d[90]), "+f"(d[91]), "+f"(d[92]), "+f"(d[93]), "+f"(d[94]), "+f"(d[95])
    : "l"(da), "l"(db), "r"(scale_d), "n"(TA), "n"(TB));
}

template<int TA, int TB>
__device__ __forceinline__ void wgmma_n48(float (&d)[24], uint64_t da, uint64_t db, int scale_d) {
  asm volatile("{\n.reg .pred p;\nsetp.ne.b32 p, %26, 0;\n"
    "wgmma.mma_async.sync.aligned.m64n48k16.f32.bf16.bf16 "
    "{%0, %1, %2, %3, %4, %5, %6, %7, %8, %9, %10, %11, %12, %13, %14, %15, %16, %17, %18, %19, %20, %21, %22, %23}, %24, %25, p, 1, 1, %27, %28;\n}\n"
    : "+f"(d[0]), "+f"(d[1]), "+f"(d[2]), "+f"(d[3]), "+f"(d[4]), "+f"(d[5]), "+f"(d[6]), "+f"(d[7]), "+f"(d[8]), "+f"(d[9]), "+f"(d[10]), "+f"(d[11]), "+f"(d[12]), "+f"(d[13]), "+f"(d[14]), "+f"(d[15]), "+f"(d[16]), "+f"(d[17]), "+f"(d[18]), "+f"(d[19]), "+f"(d[20]), "+f"(d[21]), "+f"(d[22]), "+f"(d[23])
    : "l"(da), "l"(db), "r"(scale_d), "n"(TA), "n"(TB));
}

__device__ __forceinline__ void wgmma_rs80(float (&d)[40], const uint4& a, uint64_t db, int scale_d) {
  asm volatile("{\n.reg .pred p;\nsetp.ne.b32 p, %45, 0;\n"
    "wgmma.mma_async.sync.aligned.m64n80k16.f32.bf16.bf16 {%0,%1,%2,%3,%4,%5,%6,%7,%8,%9,%10,%11,%12,%13,%14,%15,%16,%17,%18,%19,%20,%21,%22,%23,%24,%25,%26,%27,%28,%29,%30,%31,%32,%33,%34,%35,%36,%37,%38,%39}, {%40,%41,%42,%43}, %44, p, 1, 1, 1;\n}\n"
    : "+f"(d[0]), "+f"(d[1]), "+f"(d[2]), "+f"(d[3]), "+f"(d[4]), "+f"(d[5]), "+f"(d[6]), "+f"(d[7]), "+f"(d[8]), "+f"(d[9]), "+f"(d[10]), "+f"(d[11]), "+f"(d[12]), "+f"(d[13]), "+f"(d[14]), "+f"(d[15]), "+f"(d[16]), "+f"(d[17]), "+f"(d[18]), "+f"(d[19]), "+f"(d[20]), "+f"(d[21]), "+f"(d[22]), "+f"(d[23]), "+f"(d[24]), "+f"(d[25]), "+f"(d[26]), "+f"(d[27]), "+f"(d[28]), "+f"(d[29]), "+f"(d[30]), "+f"(d[31]), "+f"(d[32]), "+f"(d[33]), "+f"(d[34]), "+f"(d[35]), "+f"(d[36]), "+f"(d[37]), "+f"(d[38]), "+f"(d[39])
    : "r"(a.x), "r"(a.y), "r"(a.z), "r"(a.w), "l"(db), "r"(scale_d));
}

__device__ __forceinline__ void wgmma_ss80(float (&d)[40], uint64_t da, uint64_t db) {
  asm volatile("wgmma.mma_async.sync.aligned.m64n80k16.f32.bf16.bf16 {%0,%1,%2,%3,%4,%5,%6,%7,%8,%9,%10,%11,%12,%13,%14,%15,%16,%17,%18,%19,%20,%21,%22,%23,%24,%25,%26,%27,%28,%29,%30,%31,%32,%33,%34,%35,%36,%37,%38,%39}, %40, %41, 1, 1, 1, 0, 1;"
    : "+f"(d[0]), "+f"(d[1]), "+f"(d[2]), "+f"(d[3]), "+f"(d[4]), "+f"(d[5]), "+f"(d[6]), "+f"(d[7]), "+f"(d[8]), "+f"(d[9]), "+f"(d[10]), "+f"(d[11]), "+f"(d[12]), "+f"(d[13]), "+f"(d[14]), "+f"(d[15]), "+f"(d[16]), "+f"(d[17]), "+f"(d[18]), "+f"(d[19]), "+f"(d[20]), "+f"(d[21]), "+f"(d[22]), "+f"(d[23]), "+f"(d[24]), "+f"(d[25]), "+f"(d[26]), "+f"(d[27]), "+f"(d[28]), "+f"(d[29]), "+f"(d[30]), "+f"(d[31]), "+f"(d[32]), "+f"(d[33]), "+f"(d[34]), "+f"(d[35]), "+f"(d[36]), "+f"(d[37]), "+f"(d[38]), "+f"(d[39])
    : "l"(da), "l"(db));
}

__device__ const __align__(1024) uint32_t c_fft[11264] = {
0x2ddc2dba,0x2fe62eb5,0x2ed02eb5,0xafffaf6e,0x2e1f2dfe,0x2e3f2fbc,0x2f022ee9,0xad27af30,0x2e5e2e3f,0x1fd92b5e,0x2f302f1a,0x244ea875,0x2e992e7c,0xad96a993,0x2f5a2f46,0x2e992c32,
0xad00ad72,0xa17eac32,0xa17ea515,0xabb79cb6,0xac07ac87,0x2dfe29f1,0x1fd99648,0xafedae99,0xa9f1ab05,0x2fd42fbc,0x26a1244e,0xad96af91,0xa765a8d5,0x2aaa2e3f,0x29932875,0x2515a8d5,
0xae99adfe,0xb000aee9,0xaf6eafbc,0x2c872f30,0xaf80af1a,0xac32af02,0xae7caf02,0xaaaa217e,0xaff4afc9,0x2b5e9cb6,0xad27addc,0xaff4ae7c,0xafedb000,0x2ffc2eb5,0xab05ac5d,0xacd8af5a,
0x2c072d27,0x9fd92bb7,0xadfead00,0x2fed2e1f,0x25db2993,0xaf6eacb0,0xaf6eaed0,0x2c5d2f46,0xa5151648,0xaddcafdd,0xafffafd4,0xac321648,0xabb7a934,0x28d5a814,0xafa0afed,0xaff4af30,
0x2f302e3f,0x2fed2f1a,0x28142b5e,0x2934a875,0x30002fc9,0x26a12ddc,0xa5db1cb6,0x30002e7c,0x2f462fd4,0xaed0aa4e,0xacb0aa4e,0x29932e99,0x2d272e5e,0xae3faffc,0xaf02adfe,0xae1fa814,
0xa9f1acd8,0x26a1ab05,0x2fd42ffc,0xad96afed,0x2515a30e,0x2fff2e1f,0x2ddc2f1a,0x2c32a30e,0x2d272aaa,0x28752e7c,0x28752c32,0x2fa02f80,0x2f912e99,0xaee9a9f1,0xa8141648,0x9fd92c87,
0xafa0ae7c,0xafafaf46,0x2d002993,0xafa0ac32,0xaf91b000,0x244eac5d,0x2fbc2eb5,0xab05af5a,0xac87ae5e,0x30002dfe,0x2f6e2ffc,0x2e992814,0x1cb6a875,0x25152e1f,0x2c322e1f,0x2d722ff4,
0x27652c87,0xa9932a4e,0xaaaaadba,0xa5152c87,0xabb7a44e,0xafa0af30,0x28d59fd9,0xaff4ae5e,0xaf91ae1f,0x2814abb7,0x2ee92d00,0x1fd9ad27,0xaf5aafff,0x2fd42ed0,0x2fd42fe6,0x30002ddc,
0x2f462f6e,0x2c322fdd,0x2e7c2fdd,0xa993b000,0xab5e2934,0xafafacd8,0xad00244e,0x2f1a2dfe,0xaee9afaf,0x2f30a17e,0xadfeaff8,0xafbca30e,0x2c5da765,0xa9f12ddc,0x2d969cb6,0x2c5dacb0,
0x2bb7a993,0x2f1aa515,0x2f1a2765,0xaff4aaaa,0x2e5e2fd4,0xab052dba,0x29342f6e,0x2ee9a6a1,0xadba1fd9,0xa5dbafed,0xafddac07,0xaa4e2dfe,0xacb0aff8,0x2ddc2f02,0x9cb6ae3f,0xa765aff8,
0xaeb5af91,0xaa4eafed,0x9648ae5e,0xac5d2d4d,0x2ddca17e,0x2e7c2e3f,0x2fc92e3f,0x1cb6afa0,0x2bb72fe6,0xaff8a993,0xab5e2aaa,0x2bb72fc9,0xafbcaa4e,0x2f30a5db,0xadfeafdd,0xaee9adba,
0xacd828d5,0xaf91230e,0xaf30af02,0x2c072fa0,0xac5dafff,0x2dbaac32,0x2dbaa515,0xae99addc,0x2fc929f1,0xa9932eb5,0x2aaa2fdd,0x2fe629f1,0xa30e2dfe,0xa17eafed,0xaff8ac07,0xafaf1fd9,
0x2dfe2faf,0x28142ff8,0xae5e217e,0x2ffc230e,0xaf5aa515,0xac87af46,0xa6a1af80,0xaf5a2765,0x1cb6ae99,0x2e7c2dba,0x2fc92dba,0x2ddcac5d,0x2f1a2ee9,0xafafab05,0xad002934,0xab5e2e5e,
0x2dbaa814,0x2fdd9fd9,0x25db2f91,0x2a4eaee9,0x27652faf,0xaf4628d5,0xaf80ae1f,0xa5152faf,0xafa0addc,0x2e3fac32,0x2e3fa515,0xa17eafff,0x2dfea6a1,0xacd82dba,0x244e2f6e,0x29342fd4,
0xad27afc9,0xa30eafff,0x2faf2d72,0xad27ae7c,0x2ffc2a4e,0x28142fdd,0xae5e25db,0x2dfe2dba,0xac5d2c07,0xaa4eaf91,0x9648af30,0xaeb5acd8,0xa993aff4,0x2c322f1a,0x2e7c2f1a,0x2f462bb7,
0xae7c26a1,0xafff1648,0x2d72aa4e,0xafc926a1,0x230eaee9,0x2ff89fd9,0x217e2f91,0x2fafa814,0x2d4d2fa0,0xafed230e,0xae5eaf02,0xaf9128d5,0xb000aaaa,0x2fdda515,0x2fdd2765,0x2f6ea993,
0x9cb63000,0xacb02fd4,0xa7652fd4,0x2ddcaf5a,0x217eaffc,0x2ff4ac07,0x2875afbc,0xaff82934,0xa44e2ff4,0xadfea8d5,0xa9342fa0,0x2cd82bb7,0x25dbafe6,0x16482f46,0x29f1af80,0x25dbafc9,
0x2ff41cb6,0x2e1f2765,0x2e1f2cb0,0xa875addc,0xafbca5db,0x1fd9af5a,0xad4dad96,0xacd82fdd,0x2f5a2934,0xaeb52ee9,0x2c5d2e5e,0x3000ab05,0xaed0ab5e,0x2f80a30e,0xaaaaaf02,0xacb0ab5e,
0x25dbaffc,0x2d96afbc,0x2f5aac07,0xafdd2934,0xaaaa2fa0,0xafc92875,0xafe62875,0x29932d27,0x2d00aed0,0x28d52d72,0x2ff89cb6,0x2d00afe6,0xae5e2d96,0x2d4dafd4,0xaf91a6a1,0xafed29f1,
0xafbca17e,0xad4da875,0x1fd9aff4,0xacd82ff8,0x2e992aaa,0xaa4e2fe6,0xaa4e2fc9,0x2fd4a993,0xacb0ad96,0x2fffac87,0x2d72aeb5,0xa765ad96,0x28752f30,0xab5eac07,0xaf1a2cd8,0xae3f2f91,
0xa9342ff4,0xae5e2fa0,0xaee9a8d5,0x2b052bb7,0x2d96aed0,0x2eb59cb6,0x2c872d72,0x2d96afe6,0xaf802c5d,0x2765af6e,0xa515af6e,0xaf4625db,0x2ff8a44e,0xaff42d4d,0xa8752ffc,0xa17e2ee9,
0x2f5a244e,0x2c5d2934,0xaeb52dfe,0x3000acd8,0xacb0ad00,0x2d72aff8,0x2fffa8d5,0xa765ad00,0x217e2f80,0xaf022515,0xaf02a765,0xaf1a2f46,0x2b05afdd,0xa8142f5a,0x2c072d96,0x2d4d25db,
0x2b5eafe6,0x2f02af80,0x230e2f46,0x2b5eafc9,0xaf302d96,0xacd8a6a1,0x2c07afd4,0xaf9129f1,0x2fdda44e,0xad962ffc,0xaf5a2d4d,0xa5db2ee9,0xad72abb7,0x2e7ca17e,0x2fc9a17e,0x2fffad00,
0xaed0a5db,0xaaaaa9f1,0x2f809648,0xacb0a5db,0x28752e5e,0xaf1a2f91,0xab5ead4d,0xae3f2fed,0x2b05aff8,0x2c072875,0xa8142ff4,0x2d4d217e,0xaf6e2d72,0x2eb5afc9,0x2eb5ae7c,0x2dbaafff,
0xaf802f5a,0xafc92e99,0xafe62e99,0x2f46ad96,0x28d52b05,0xaf022fed,0x230e2cd8,0x2fa0affc,0x2fbcaf02,0xa9342d27,0x2ffcae1f,0x2c07ae3f,0xa6a1ac32,0x2a4e9cb6,0x9648ad72,0xa6a1a515,
0x28752aaa,0xa8d52cb0,0xa8d52ed0,0x2e3faf80,0x2fedaeb5,0x29349648,0x2f30aa4e,0x2814ac5d,0x1648ad4d,0x2e99acd8,0x2c87afbc,0xa9f11fd9,0xafe62d27,0x2fffafaf,0xaddc230e,0xaed02d27,
0x2fd4af30,0x2f6eae5e,0x2dbaa44e,0xa6a19fd9,0x1cb6ad27,0x2fe6aff4,0x2ed0aff4,0xad722b5e,0xafaf2cb0,0x2e1faf46,0xa8d5a993,0xafaf2ed0,0xac072f6e,0x2934ac87,0xaffc2e99,0xafbc3000,
0xa44eab5e,0x2b05ad00,0x2f91afaf,0xafbc2f1a,0xafd42d72,0x1648a765,0x1648acb0,0xafdd2fff,0xac322f5a,0xaaaa26a1,0xaf802c87,0xae7c2f5a,0x2d009fd9,0xae1f2cd8,0xad272fbc,0xabb72d4d,
0xaffc2f02,0xaee92e1f,0x244ead27,0xad4d2e3f,0xa9f12e7c,0xafdd2f80,0xaeb52aaa,0xa9f12c32,0x2d72a5db,0xafe63000,0xaed03000,0x9cb626a1,0x2fa0afbc,0xaf022f91,0x230e2b05,0x28d5a44e,
0x96482c07,0xac872d4d,0xae992b05,0x29f1a814,0x2ed0abb7,0xa9932b5e,0xaf462ff8,0x2cb0abb7,0x2f1aafff,0xa30e2765,0xa30e2cb0,0x2e1fad72,0x1fd9ac5d,0x244e9648,0x2e5eaa4e,0x2f30aeb5,
0x2ff8aed0,0x2e3faddc,0xaf022fff,0x2ff8afe6,0x2d4daf6e,0x2ee9ae99,0xa44e2c87,0x2ffcb000,0xa6a1a814,0x2f6eaf30,0x2dbaa934,0x2fd4afed,0xaf462d00,0x2fc9afa0,0x2fe6afa0,0x2f80afaf,
0x2515ac5d,0x2d72ad96,0x1cb629f1,0x2c32ac5d,0xad002814,0x2d27ad4d,0x2e1fab05,0x2bb7ac07,0xaffc2f1a,0x2cd8ad00,0x2fedafaf,0x2b05ab5e,0xadba2f80,0x2c87acb0,0x2c87aed0,0x2a4eaaaa,
0x2f802f6e,0x2fc92fdd,0x2fe62fdd,0xaf46b000,0x2fa02f91,0x2bb72e5e,0x2ff42fed,0xa8d5ad4d,0x2fbc2faf,0xa934217e,0x2ffc2ff8,0x2c07230e,0x2fd42fc9,0xaf5aad72,0x30002fff,0x2fd42e7c,
0x2bb72aaa,0x2f1a2cb0,0x2f1a2ed0,0xaff4af80,0x2cd82c5d,0x2f303000,0x2f912f5a,0xac07aeb5,0x2dba2d4d,0x25db2cd8,0x2fdd2fbc,0x2a4e9fd9,0x2e7c2e1f,0xad72a875,0x2fff2ff4,0x2fc92e1f,
0xa6a1a934,0x29f1a44e,0x2d962cd8,0xafd4adfe,0x1cb6a17e,0x2fe62e3f,0x2ed02e3f,0xad72afa0,0x28752515,0x2d272f80,0x2fa02f46,0x2875a765,0x2c072a4e,0xa93425db,0x2ffc2fdd,0x2fbc2dba,
0xae5eaf1a,0xa934ae3f,0x2b052875,0xaee9ab5e,0xac5dad72,0x2dba2765,0x2dba2cb0,0xae99afff,0xa765aa4e,0x2f802fd4,0x2f462e99,0x2515aa4e,0x230e9fd9,0x217e2cd8,0x2ff82fbc,0x2faf2d4d,
0xaffcafaf,0xaee9aff8,0x244ea17e,0xad4da30e,0xaf6eafe6,0x25dbaaaa,0x2c5d2993,0xaf6eafc9,0xad72ae99,0x2fe62dba,0x2ed02dba,0x1cb6ac5d,0xa8d5ac07,0x2bb72f30,0x2ff42f91,0x2fa02cd8,
0xadbaac07,0xafddad4d,0xa5dbab05,0xaa4e2814,0xafc9af02,0xaaaaaf1a,0x2993217e,0xafe6af02,0xafa0afff,0x2e3f2765,0x2e3f2cb0,0xa17ead72,0xad4daeb5,0x2e5e3000,0x2fed2f5a,0x2f912c5d,
0xa17e2765,0xad001cb6,0xabb7addc,0xa17e2cb0,0xad4daa4e,0xaee9afdd,0x244ea5db,0xaffcadba,0xafd4aee9,0x29f1a934,0x2d962b05,0xa6a1ae5e,0xaf46aff4,0x2fc92f1a,0x2fe62f1a,0x2f802bb7,
0x2cb02eb5,0x1cb62dba,0xaddcaf6e,0x27652eb5,0xa30e2814,0xaff8ad4d,0xa17eab05,0xafafac07,0xadfeab5e,0xa44eae3f,0x2cd82875,0xa934af1a,0xb000af80,0x2fdd2cb0,0x2fdd2ed0,0x2f6e2aaa,
0x2d723000,0x25152fd4,0x2c322fd4,0x1cb6af5a,0xae1f9fd9,0xae3faee9,0xaf02a814,0x2d272f91,0xacd8aff4,0x2ffc28d5,0xab05afa0,0xafedabb7,0x2e992515,0xad962aaa,0x2f5a2993,0x2e99a765,
0x2ff42ddc,0x2e1f2ed0,0x2e1f2fe6,0xa875afff,0xa8142c87,0xaffca9f1,0xadfe1648,0x2e5e2e99,0xaf5aaf30,0x2eb5a814,0xac5dafed,0xb000a934,0x2c32a8d5,0xa9932e3f,0x2f462875,0x2e7ca8d5,
0x2e991fd9,0x30002814,0x2f6e2ee9,0xac87af91,0x29932fa0,0xaed02875,0xacb02875,0x2f462d27,0xaff4ac32,0x2b5eaddc,0xad27afff,0xaff4a515,0x244ead96,0x1fd92fd4,0x2f3026a1,0x2e5ea9f1,
0x2814ad27,0x2dfeabb7,0x2ffc2d00,0xae5eae1f,0x2e992f80,0xaa4e2e7c,0xaa4e2c32,0x2fd42aaa,0xae7c1648,0x9cb6afdd,0xaddcafd4,0xafc91648,0xa875af91,0x2b5e2fbc,0x2f1a244e,0x2e3fab05,
0xab05aff4,0x244eafa0,0x2fbc28d5,0xaf91abb7,0x30002c32,0x26a12fff,0xa5db2ddc,0x30002515,0xaaaa2c5d,0xac32af6e,0xae7caf6e,0xaf8025db,0xad27afed,0x2e3f2dfe,0x2f021fd9,0x2e1fac07,
0xaf5aae5e,0xac5daf30,0x2eb59fd9,0xb000a44e,0x2e7ca30e,0x2ddc2e1f,0x1cb62f1a,0x2fc9a30e,0x217e2f46,0xaf02acb0,0xaf02aed0,0xaf1a2993,0xaf30ae99,0x2fbc29f1,0x2ee99648,0x2dfeac87,
0xafa0a515,0xafafa993,0x2d00aaaa,0xafa02765,0x2934ad96,0x2fed26a1,0x28142fd4,0x2f30a9f1,0x2c872fed,0xb0009fd9,0xaf6eadfe,0xae992c07,0xafffabb7,0x2fe6a17e,0x2ed0a17e,0x2ddcad00,
0xac322c87,0xaf462a4e,0x2993adba,0xae7c2c87,0xa875afed,0x2f1aab05,0x2b5e2ffc,0x2e3facd8,0x2f302e1f,0xaee92bb7,0xafbcad00,0xadfe2d27,0xaf6e9cb6,0x2eb5ac32,0x2eb5a515,0x2dbaad72,
0xaaaa2f5a,0xaed02e99,0xacb02e99,0x2f80ad96,0x2b5eaf30,0x2fafa44e,0x2d00ae5e,0xaf1a9fd9,0xac072f02,0xab05ad27,0xad4d2e1f,0x28142e3f,0x2c5daed0,0xa9f12fff,0x2d96addc,0x2c5dafe6,
0x28752f80,0xa8d52fe6,0xa8d52fc9,0x2e3faf46,0xa44eafd4,0x2f91adba,0x2b05af6e,0xafbc26a1,0x96482ffc,0xae99a44e,0xac872ee9,0x29f12d4d,0x2515aff8,0x1cb62f02,0x2d72ae3f,0x2c32aff8,
0x2eb52b05,0x2a4e2cd8,0x16482fed,0x2c5daffc,0xad72ad27,0x2cb0aff4,0x2765aff4,0xafff2b5e,0x2bb72e7c,0xaff82aaa,0xab5e2f80,0x2bb72c32,0xa814af6e,0x2b052c87,0x2d4dae99,0x2c07b000,
0x2feda8d5,0x2f30a30e,0x29342f02,0x2814afa0,0xafd49cb6,0x1648aed0,0x1648afe6,0xafdd2d72,0x2ed029f1,0xaf462eb5,0xa9932fdd,0x2cb029f1,0xad00ad4d,0x2e1f244e,0x2d27aee9,0x2bb7affc,
0x2d4daf02,0x2fbcae1f,0x2cd82d27,0x9fd9ae3f,0xaf5a2cb0,0xac87a993,0xa6a1af46,0xaf5a2ed0,0x2fffa5db,0xacb03000,0xa7653000,0x2d7226a1,0xaf1aa814,0x2fafa934,0x2d00af30,0x2b5eafed,
0x1648afbc,0x2c87affc,0x2e992934,0xa9f1ac07,0xac322faf,0xaf8028d5,0xaaaaae1f,0xae7c2faf,0x2f1aad72,0xa30e2ed0,0xa30e2fe6,0x2e1f1cb6,0xaffc26a1,0x2fedadba,0x2cd8af6e,0x2b05afd4,
0xad27ac32,0xa30ead72,0x2faf9cb6,0xad27a515,0x1fd92f6e,0xafbc2e99,0xacd8ac87,0xad4d3000,0x2c5dafbc,0x2a4e2b05,0x16482f91,0x2eb5a44e,0xaf802d00,0x2ed0afa0,0x2cb0afa0,0x2aaaafaf,
0xafe626a1,0xaddc1648,0x2fffaa4e,0xaed026a1,0x2d002c07,0xad272ffc,0xae1fa934,0xabb72fbc,0x1fd9afa0,0x2e5ea30e,0x244e2f02,0x2f30a8d5,0xadba2f46,0x2c87afe6,0x2c87afc9,0x2a4eaf80,
0xafff2d96,0xae7c2c5d,0xafc92c5d,0x2d72a9f1,0xa17e2dfe,0xaff42fbc,0xa8752ee9,0x2ff8af30,0x2fedad00,0xad4d2f1a,0x2f91ab5e,0x2e5eafaf,0x25dbae7c,0x16482993,0x29f1af46,0x25dbac32,
0xae3f2fff,0xaff82fc9,0xaff82e7c,0x2f02ad72,0x2c0725db,0xadfe2f5a,0x9fd92d96,0x2fedafdd,0x2f6eaf91,0xa6a12c07,0x2fd4acd8,0x2dbaaf30,0xa765ab5e,0x2aaaa30e,0x2993af02,0x2515ab5e,
0xa5db2dfe,0xad962ee9,0xaf5a2fbc,0x2fddaf30,0x2f46ab5e,0xa7652bb7,0x25152bb7,0x2f80aff8,0x2d00afc9,0x28d59cb6,0x2ff8addc,0x2d00ae7c,0xacd89648,0x2dfeac5d,0x2934aeb5,0x244eaa4e,
0x2c07217e,0x9fd92875,0xadfe2ff4,0x2fedaff8,0x2fddaf46,0x29f1a515,0x29f12765,0x2eb5af80,0x2515ad96,0x2ddcac87,0x2fffaeb5,0x2c32ad96,0xaf022b05,0x2fa0aee9,0x28d5ae5e,0x230ea934,
0x2f91ad00,0x2cd8ab5e,0xac072f1a,0x2f30afaf,0x2d96afc9,0x2eb5addc,0x2c879cb6,0x2d96ae7c,0xa993a6a1,0x2fc9af5a,0x2fe6af5a,0x2aaaac87,0xaff82e5e,0x2ff4affc,0x2875adfe,0x217ea814,
0x2f6eafed,0x2fd4af91,0xa6a12d4d,0x2dbaae5e,0x2515ad00,0x2fffaff8,0x2ddca8d5,0x2c32ad00,0xae1f2993,0x2fafafe6,0x2fafafc9,0x28d5aaaa,0xaf912fdd,0x2ee9af5a,0x2814ad96,0x1fd9a5db,
0x2b5eae7c,0x2f02af46,0x230e2993,0x2b5eac32,0xab059648,0x2e5eaeb5,0x2ee9ac5d,0x2934aa4e,0xafdd2e5e,0x2d96adfe,0x2f5aaffc,0x25dba814,0xaddc2faf,0x2cb0ad27,0x2765ad27,0x1cb6a30e,
0xa765a5db,0x2993a9f1,0x2aaa9648,0x2515a5db,0xaf022cd8,0x28d5a934,0x2fa0adfe,0x230ea44e,0xaf912ff8,0x2814a875,0x2ee9aff4,0x1fd9a17e,0xaa4e2ddc,0x26a1a765,0x26a1acb0,0x16489cb6,
0x2d722d96,0x25152c5d,0x2c322c5d,0x1cb6a9f1,0x2d272d4d,0xad00a814,0x2bb72c07,0x2e1f2b05,0x2cd82d00,0xaffcaf1a,0x2b052b5e,0x2fed2faf,0x2c872cb0,0xadbaaf80,0x2a4e2aaa,0x2c872ed0,
0x2e3f2ddc,0x2ff82ed0,0x2ff82fe6,0xaf02afff,0x2ee92e99,0x2d4d2f6e,0x2ffc3000,0xa44eac87,0x2f6e2f30,0xa6a12814,0x2fd42fed,0x2dba2934,0x2fc92fa0,0xaf46ad00,0x2f802faf,0x2fe62fa0,
0xac87ad4d,0x9648ac07,0x29f12814,0xae99ab05,0xa993ab5e,0x2ed02bb7,0x2cb02bb7,0xaf46aff8,0xa30ea765,0x2f1a2fff,0x2e1f2d72,0xa30eacb0,0x244e1648,0x1fd92c5d,0x2f302eb5,0x2e5e2a4e,
0xaee9ae1f,0xaffcaf02,0xad4dae3f,0x244e2d27,0xafddaf80,0xa9f1ae7c,0xa9f1ac32,0xaeb5aaaa,0xafe6b000,0x2d7225db,0x9cb6a6a1,0xaed0b000,0xaf02af91,0x2fa02fbc,0x28d5244e,0x230eab05,
0x2b052d00,0xa44e2b5e,0xafbcaf1a,0x2f912faf,0x16482765,0xafd4ad72,0xafddafff,0x16482cb0,0xaaaaa6a1,0xac32af5a,0xae7caf5a,0xaf80ac87,0xae1facd8,0x2d001fd9,0xabb7ad4d,0xad27afbc,
0x2f6e2e5e,0x2fd42f30,0xa6a11fd9,0x2dba244e,0x2fe62ff4,0x1cb62d27,0xad72ab5e,0x2ed02ff4,0x2e1f2f46,0xafafacb0,0xafafaed0,0xa8d52993,0x29342c87,0xac07af6e,0xafbcb000,0xaffcae99,
0xa8d5acb0,0x2875aaaa,0x2e3f2f80,0xa8d5aed0,0x29341648,0x2fed2eb5,0x28142c5d,0x2f302a4e,0x2e992cd8,0x16482d4d,0xa9f19fd9,0x2c872fbc,0x2fff2faf,0xafe6ad27,0xaed0ad27,0xaddca30e,
0xafc9ae99,0xaf80af5a,0x2f462d96,0xafe6ae99,0xaf02afed,0x28d5ab05,0x2fa02ffc,0x230eacd8,0xa934ad27,0x2fbc2f02,0x2c072e3f,0x2ffc2e1f,0x2a4e1cb6,0xa6a12c32,0xa6a12515,0x96482d72,
0xaaaa29f1,0xaed025db,0xacb025db,0x2f801648,0xaf1aaf91,0x2875ae5e,0xae3fafed,0xab5e2d4d,0x2c07a875,0x2b052ff8,0x2d4da17e,0xa814aff4,0x2eb52fc9,0xaf6ead72,0x2dba2fff,0x2eb52e7c,
0x2f022f80,0x2b5e2fe6,0x2b5e2fc9,0x230eaf46,0xacd826a1,0xaf30ad96,0xaf91a9f1,0x2c072fd4,0xad96affc,0x2fdd244e,0xa5dbaee9,0xaf5aad4d,0x2e7c217e,0xad722bb7,0x2fff2d00,0x2fc9217e,
0x2c5da934,0x2f5aa44e,0x30002cd8,0xaeb5adfe,0x2d722ff8,0xacb02d00,0xa7652d00,0x2fff28d5,0xaf02a515,0x217eaf80,0xaf1aaf46,0xaf022765,0xa814af5a,0x2b052fdd,0x2d4da5db,0x2c07ad96,
0xae5eafa0,0xa934aff4,0x2b05abb7,0xaee928d5,0x2eb51cb6,0x2d962ed0,0x2d962fe6,0x2c87ad72,0x27652f6e,0xaf80ac5d,0xaf46a5db,0xa5152f6e,0xaff4ad4d,0x2ff8244e,0xa17eaee9,0xa875affc,
0xad4d2875,0xafbc217e,0xacd8aff8,0x1fd92ff4,0xaa4eafe6,0x2e99aaaa,0x2fd42993,0xaa4eafc9,0x2fff2c87,0xacb02d96,0xa7652d96,0x2d722eb5,0xab5e2c07,0x2875af30,0xae3faf91,0xaf1aacd8,
0x2d962fbc,0x25db2ffc,0xafdda934,0x2f5a2c07,0xafc9a875,0xaaaaafa0,0x2993ad27,0xafe6a875,0x28d5ad72,0x2d002ed0,0x2d002fe6,0x2ff81cb6,0x2d4d2fd4,0xae5ead96,0xafeda9f1,0xaf9126a1,
0x2e1fa765,0x2ff49cb6,0xa8752ddc,0x2e1facb0,0x1fd92f5a,0xafbc25db,0xacd8afdd,0xad4d2d96,0xaeb5aee9,0x2f5aa934,0x30002b05,0x2c5dae5e,0x2f80230e,0xaed02b5e,0xacb02b5e,0xaaaa2f02,
0xacb0afd4,0x9cb6b000,0x2ddc2f5a,0xa765afd4,0x2ff42c07,0x217e2ffc,0xaff8a934,0x28752fbc,0xadfe28d5,0xa44eaff4,0x2cd8abb7,0xa934afa0,0x1648af46,0x25db2fe6,0x25db2fc9,0x29f12f80,
0xafff9648,0xae7ca6a1,0xafc9a6a1,0x2d722a4e,0x2ff81fd9,0x230e2ee9,0x2faf2814,0x217eaf91,0xafeda30e,0x2d4dafa0,0xaf91a8d5,0xae5e2f02,0x2fdd2515,0xb0002aaa,0x2f6e2993,0x2fdda765,
0xa30e2fff,0xad272fc9,0xad272e7c,0x2fafad72,0x2814afdd,0x2ffcaa4e,0x2dfeadba,0xae5ea5db,0xaa4e2f91,0xac5dac07,0xaeb52cd8,0x96482f30,0x2c32af1a,0xa9932ff4,0x2f46abb7,0x2e7caf1a,
0x2fdd1fd9,0x2dba2814,0x2a4e2ee9,0x25dbaf91,0xaf46a8d5,0x2765afaf,0xa515afaf,0xaf802e1f,0x2e3f2c32,0xafa02ddc,0xa17e2fff,0x2e3f2515,0xacd8adba,0x2dfe26a1,0x2934afd4,0x244eaf6e,
0x2814aff8,0x2dfeafaf,0x2ffca30e,0xae5ea17e,0xac872f46,0xaf5a2515,0xaf5aa765,0xa6a12f80,0x2e7cadba,0x1cb62e99,0x2ddc2c5d,0x2fc9adba,0xafaf2b05,0x2f1aaee9,0xab5eae5e,0xad00a934,
0xaf91a30e,0xacd8a8d5,0x2c07afa0,0xaf302f02,0x2dba2c32,0xac5d2fff,0xae992ddc,0x2dba2515,0xa993aeb5,0x2fc9a9f1,0x2fe6a9f1,0x2aaaafdd,0xa17e2fed,0xa30eadfe,0xafaf9fd9,0xaff82c07,
0xaa4e2fed,0xaeb52f91,0xac5dad4d,0x96482e5e,0x2e7cae3f,0x2ddc217e,0x1cb62fa0,0x2fc9ae3f,0xaff82993,0x2bb7afe6,0x2bb7afc9,0xab5eaaaa,0x2f3025db,0xafbc2a4e,0xaee92dba,0xadfe2fdd,
0x2f1a2515,0x2bb72993,0xaff42aaa,0x2f1aa765,0xab05adba,0x2e5eafd4,0x2ee926a1,0x2934af6e,0xa5db2fed,0xadba9fd9,0xaa4eadfe,0xafdd2c07,0x2ddcaf02,0xacb02ff8,0xa7652ff8,0x9cb62e3f,
0x2c32afdd,0x2f46af6e,0xa9933000,0x2e7cafdd,0xafaf2cd8,0xab5ea934,0x2f1aadfe,0xad00a44e,0x2f30217e,0xaee92faf,0xafbc230e,0xadfe2ff8,0xa9f1addc,0x2c5d2765,0x2c5d2cb0,0x2d961cb6,
0xa993aa4e,0x2765ac87,0xa515ac87,0xaaaa2dba,0xafa02f30,0xabb7244e,0xaff42e5e,0x28d51fd9,0x28142bb7,0xaf912e1f,0x1fd92d27,0x2ee9ad00,0x2fd4aed0,0xaf5a2fff,0x3000addc,0x2fd4afe6,
0xafaf2f46,0xafa02e7c,0xafa02c32,0x2d00a993,0x244e2c5d,0xaf913000,0xab052f5a,0x2fbcaeb5,0x3000adfe,0xac872e5e,0x2e99a814,0x2f6eaffc,0x2515ae1f,0x1cb62875,0x2d72aff4,0x2c32ae1f,
0x26a12b05,0xa9f12cd8,0xad962fed,0x2fd4affc,0x2fffae1f,0x2515230e,0x2c32230e,0x2ddcaf1a,0x2875ae7c,0x2d27aaaa,0x2fa0af80,0x2875ac32,0xaee929f1,0x2f91ae99,0x9fd9ac87,0xa8149648,
0x2fedaf1a,0x2f30ae3f,0x29342875,0x2814ab5e,0x26a1addc,0x3000afc9,0x3000ae7c,0xa5db9cb6,0xaed02a4e,0x2f46afd4,0x2993ae99,0xacb02a4e,0xae3f2ffc,0x2d27ae5e,0xae1f2814,0xaf022dfe,
0x9fd9abb7,0x2c07ad27,0x2fedae1f,0xadfe2d00,0xaf6e2cb0,0x25dba993,0x2c5daf46,0xaf6e2ed0,0xaddc2fdd,0xa5159648,0xac329648,0xafff2fd4,0x28d52814,0xabb72934,0xaff42f30,0xafa02fed,
0xb0002ee9,0xae992dfe,0x2c87af30,0xaf6e2fbc,0xac322f02,0xaf802f1a,0xaaaaa17e,0xae7c2f02,0x2b5e1cb6,0xaff42fc9,0xaff42e7c,0xad272ddc,0x2ffcaeb5,0xafed3000,0xacd82f5a,0xab052c5d,
0xa17e2c32,0xad002d72,0xabb71cb6,0xa17e2515,0x2dfea9f1,0xac072c87,0xafed2e99,0x1fd91648,0x2fd4afbc,0xa9f12b05,0xad962f91,0x26a1a44e,0x2aaaae3f,0xa76528d5,0x251528d5,0x2993a875,
0x2fe6aeb5,0x2ddcadba,0xafff2f6e,0x2ed0aeb5,0x2e3fafbc,0x2e1fadfe,0xad272f30,0x2f02aee9,0x1fd9ab5e,0x2e5eae3f,0x244e2875,0x2f30af1a,0xad962993,0x2e99ae7c,0x2e99ac32,0x2f5aaf46,
0x299329f1,0xa76525db,0x251525db,0x2aaa1648,0x28d52934,0xaf02acd8,0x230e244e,0x2fa02dfe,0x28142875,0xaf91aff8,0x1fd9217e,0x2ee92ff4,0x26a12765,0xaa4eaddc,0x16481cb6,0x26a12cb0,
0x2f022f46,0x2b5e2e7c,0x2b5e2c32,0x230ea993,0x2e5e2eb5,0xab051648,0x29342a4e,0x2ee92c5d,0x2d962dfe,0xafddae5e,0x25db2814,0x2f5a2ffc,0x2cb02d27,0xaddcafaf,0x1cb6230e,0x27652d27,
0x2fd42f91,0x2f6e2fed,0x2dba2e5e,0xa6a1ad4d,0x2fff2ff8,0x25152d00,0x2c322d00,0x2ddc28d5,0x2faf2fe6,0xae1fa993,0x28d52aaa,0x2faf2fc9,0x2ee92f5a,0xaf91afdd,0x1fd925db,0x28142d96,
0x2cd82b5e,0x2f912d00,0x2f302faf,0xac07af1a,0x2eb52ddc,0x2d962fc9,0x2d962e7c,0x2c871cb6,0x2fc92f5a,0xa99326a1,0x2aaa2c87,0x2fe62f5a,0x2ff42ffc,0xaff8ae5e,0x217e2814,0x28752dfe,
0x9fd9a875,0x2c07a17e,0x2fed2ff8,0xadfeaff4,0x29f12515,0x2fdd2f46,0x2eb52f80,0x29f1a765,0x2ddc2c87,0x25152d96,0x2c322d96,0x2fff2eb5,0x2fa02ee9,0xaf02ab05,0x230e2934,0x28d52e5e,
0xad96aee9,0xa5dbadfe,0x2fdd2f30,0xaf5aafbc,0xa765abb7,0x2f462b5e,0x2f802ff8,0x2515abb7,0x28d51cb6,0x2d002fc9,0x2d002e7c,0x2ff82ddc,0x2dfe2c5d,0xacd81648,0x244e2a4e,0x29342eb5,
0xaff8afc9,0xae3fafff,0x2f022d72,0xaff8ae7c,0xadfeaf5a,0x2c07a5db,0x2fed2fdd,0x9fd9ad96,0xa6a1ac07,0x2f6e2f91,0x2dba2f30,0x2fd42cd8,0x2aaa230e,0xa7652b5e,0x25152b5e,0x29932f02,
0xae7cac5d,0xafffad96,0x2d7229f1,0xafc9ac5d,0xaff4afbc,0xa17eadfe,0x2ff82f30,0xa875aee9,0xad4daf1a,0x2fed2d00,0x2e5e2faf,0x2f912b5e,0x1648a993,0x25db2e7c,0x25db2c32,0x29f12f46,
0xaddc9648,0xafe6a6a1,0xaed0a6a1,0x2fff2a4e,0xad27affc,0x2d00ac07,0xabb7afbc,0xae1f2934,0x2e5e230e,0x1fd92fa0,0x2f3028d5,0x244eaf02,0x2c872fe6,0xadbaaf46,0x2a4e2f80,0x2c872fc9,
0xa30e2d72,0xad272c32,0xad272515,0x2faf1cb6,0xafbcae99,0x1fd9af6e,0xad4db000,0xacd82c87,0x2a4eab05,0x2c5d2fbc,0x2eb5244e,0x1648af91,0x2ed02fa0,0xaf80ad00,0x2aaa2faf,0x2cb02fa0,
0x2c872ffc,0x16482fbc,0xa9f12c07,0x2e99a934,0xaf80a8d5,0xac32afaf,0xae7cafaf,0xaaaa2e1f,0xa30eaed0,0x2f1a2d72,0x2e1f9cb6,0xa30eafe6,0x2fed2dba,0xaffca6a1,0x2b052fd4,0x2cd82f6e,
0x2fbc2e1f,0x2d4d2f02,0x9fd92e3f,0x2cd8ad27,0xac872993,0xaf5aacb0,0xaf5aaed0,0xa6a12f46,0xacb0b000,0x2fff25db,0x2d72a6a1,0xa765b000,0x2faf2934,0xaf1a2814,0x2b5e2fed,0x2d002f30,
0x2f30230e,0x2fed28d5,0x28142fa0,0x2934af02,0x16482ed0,0xafd41cb6,0xafddad72,0x16482fe6,0xaf46aeb5,0x2ed0a9f1,0x2cb0a9f1,0xa993afdd,0x2e1fa44e,0xad002d4d,0x2bb72ffc,0x2d272ee9,
0x2a4eacd8,0x2eb5ab05,0x2c5d2ffc,0x1648afed,0x2cb02ff4,0xad722d27,0xafffab5e,0x27652ff4,0xaff8aaaa,0x2bb7ae7c,0x2bb7ac32,0xab5eaf80,0x2b05ac87,0xa8142f6e,0x2c073000,0x2d4d2e99,
0xa8d5afe6,0x2875af80,0x2e3f2f46,0xa8d5afc9,0x2f912dba,0xa44e2fd4,0xafbca6a1,0x2b052f6e,0xae99244e,0x9648affc,0x29f1ad4d,0xac87aee9,0x1cb6af02,0x25152ff8,0x2c322ff8,0x2d722e3f,
0xaed0ae99,0xaaaaaf5a,0x2f802d96,0xacb0ae99,0x2faf244e,0x2b5e2f30,0xaf1a1fd9,0x2d002e5e,0xab052d27,0xac07af02,0x2814ae3f,0xad4dae1f,0xa9f1afff,0x2c5d2ed0,0x2c5d2fe6,0x2d962ddc,
0xaf46aa4e,0xac32ac87,0xae7cac87,0x29932dba,0x2f1a2b05,0xa8752fed,0x2e3f2cd8,0x2b5eaffc,0xaee9abb7,0x2f30ae1f,0xadfead27,0xafbc2d00,0x2eb52c32,0xaf6e1cb6,0x2dba2d72,0x2eb52515,
0xafaf2993,0xafa02515,0xafa0a765,0x2d002aaa,0x2feda6a1,0x29342d96,0x2f3029f1,0x2814afd4,0xb0001fd9,0x2c87afed,0xae99ac07,0xaf6e2dfe,0x2fe6217e,0xafff2bb7,0x2ddc2d00,0x2ed0217e,
0xac5d2f30,0xaf5a2e5e,0xb000244e,0x2eb51fd9,0x2ddcae1f,0x2e7c230e,0x2fc9230e,0x1cb6af1a,0xaf022cb0,0x217eaf46,0xaf1aa993,0xaf022ed0,0x2fbca9f1,0xaf302e99,0x2dfe2c87,0x2ee91648,
0x244e2fa0,0xab052ff4,0xaf912bb7,0x2fbca8d5,0x26a1afff,0x3000ac32,0x3000a515,0xa5dbaddc,0xac322f6e,0xaaaaac5d,0xaf80a5db,0xae7c2f6e,0x2e3fadfe,0xad272fed,0x2e1f2c07,0x2f029fd9,
0x2dfe2bb7,0x28142d27,0xae5e2e1f,0x2ffcad00,0xaa4eae7c,0x2e99af80,0x2fd4aaaa,0xaa4eac32,0x9cb62fdd,0xae7c9648,0xafc99648,0xaddc2fd4,0x2b5eafbc,0xa8752f91,0x2e3f2b05,0x2f1aa44e,
0x3000a814,0x2e999fd9,0xac872f91,0x2f6eaee9,0xaed0a875,0x2993afa0,0x2f46ad27,0xacb0a875,0x2b5e2ddc,0xaff42c32,0xaff42515,0xad272fff,0x1fd9afd4,0x244e2d96,0x2e5e29f1,0x2f30a6a1,
0x2e1faed0,0x2ff4addc,0xa8752fff,0x2e1fafe6,0xaffc29f1,0xa814ac87,0x2e5eae99,0xadfe9648,0x2eb52814,0xaf5a2f30,0xb0002934,0xac5d2fed,0xa993ae3f,0x2c3228d5,0x2e7c28d5,0x2f46a875,
0x2515afd4,0x2d72b000,0x1cb62f5a,0x2c32afd4,0xae3f2ee9,0xae1f1fd9,0x2d27af91,0xaf022814,0x2ffca8d5,0xacd82ff4,0xafed2bb7,0xab052fa0,0xad96aaaa,0x2e99a515,0x2e992765,0x2f5aa993,
0x1cb6adba,0x2cb0aeb5,0x2765aeb5,0xaddc2f6e,0xaff82d4d,0xa30ea814,0xafaf2c07,0xa17e2b05,0xa44e2e3f,0xadfe2b5e,0xa9342f1a,0x2cd8a875,0x2fddacb0,0xb0002f80,0x2f6eaaaa,0x2fddaed0,
0xad009cb6,0xa17ea765,0xa17eacb0,0xabb72ddc,0xaee92fdd,0xad4d2a4e,0xaffc2dba,0x244e25db,0x29f12934,0xafd42ee9,0xa6a12e5e,0x2d96ab05,0x2fc9af1a,0xaf462ff4,0x2f80abb7,0x2fe6af1a,
0xafdd2d4d,0xadba2c07,0xaa4ea814,0xa5db2b05,0xaaaa2f1a,0xafc92f02,0xafe62f02,0x2993a17e,0x2e3fa765,0xafa02fff,0xa17e2d72,0x2e3facb0,0x2e5eb000,0xad4d2eb5,0x2f91ac5d,0x2fedaf5a,
0xaee92ff8,0xaffc2faf,0xad4d230e,0x244e217e,0x25db2aaa,0xaf6e2fe6,0xaf6e2fc9,0x2c5da993,0x2fe6adba,0xad722e99,0x1cb62c5d,0x2ed0adba,0x2bb7af30,0xa8d52c07,0x2fa0acd8,0x2ff4af91,
0xa9342e3f,0xae5e2f1a,0xaee92b5e,0x2b05a875,0x2dbaa765,0xac5d2d72,0xae992fff,0x2dbaacb0,0x2f80afd4,0xa7652a4e,0x25152a4e,0x2f46ae99,0x217eacd8,0x230e1fd9,0x2fafad4d,0x2ff8afbc,
0x29f1244e,0xa6a12934,0xafd42dfe,0x2d96acd8,0x2fe6ae3f,0x1cb6217e,0xad722fa0,0x2ed0ae3f,0x2d27af80,0x2875a515,0x28752765,0x2fa0af46,0xa934a5db,0x2c07aa4e,0x2fbcadba,0x2ffcafdd,
0x2f1aacb0,0x2bb7aaaa,0xaff42f80,0x2f1aaed0,0x2f30b000,0x2cd8ac5d,0xac072eb5,0x2f91af5a,0x25dbacd8,0x2dbaad4d,0x2a4e1fd9,0x2fddafbc,0xad722875,0x2e7cae1f,0x2fc9ae1f,0x2fffaff4,
0x2fc9afdd,0x2f80af6e,0xaf463000,0x2fe6afdd,0x2bb7ae5e,0x2fa0af91,0xa8d52d4d,0x2ff4afed,0xa934a17e,0x2fbcafaf,0x2c07a30e,0x2ffcaff8,0xaf5a2d72,0x2fd4afc9,0x2fd4ae7c,0x3000afff,
0x9d4d9e16,0xada6ae7d,0x9b769c84,0xabf0accf,0x985299e4,0xa897aa43,0x90b6957f,0xa102a5d8,0x13db0a48,0x242c1aad,0x191b1712,0x296d2783,0x1c201aad,0x2c632b1a,0x1db21ce9,0x2e112d3a,
0xa3f4a491,0xae51af42,0xa199a2c6,0xac70ad60,0x9e7ba06b,0xa922ab00,0x97129c20,0xa199a688,0x19e410b6,0x24aa1b76,0x1fa81d4d,0x2a112833,0x222f2102,0x2ce82bf0,0x2445235d,0x2ec92dd8,
0xa6a1a79c,0xaefcb004,0xa4aaa5a5,0xace8adf2,0xa166a35d,0xa9acabbe,0x99e49edf,0xa22fa738,0x1ce913db,0x25281c20,0x2262206b,0x2ab528a4,0x2528242c,0x2d6d2c63,0x271f2623,0x2f822e77,
0xa8a4a954,0xafa8b067,0xa688a7e8,0xad60ae84,0xa38fa528,0xaa37ac3d,0x9c20a0d0,0xa2c6a7e8,0x1edf157f,0x25a51c84,0x2478222f,0x2b592915,0x273825d8,0x2df22ccf,0x28fc284c,0x301d2f16,
0xa9f8aadb,0xb02ab0ca,0xa833a915,0xadd8af16,0xa4dca6a1,0xaac1ac9c,0x9d4da22f,0xa35da84c,0x206b1712,0x26231ce9,0x25bf23f4,0x2bfd2987,0x28a42783,0x2e772d3a,0x2a692987,0x307a2fb5,
0xab4cac31,0xb081b12e,0xa922aa37,0xae51afa8,0xa5f1a80d,0xab4cacfb,0x9e7ba38f,0xa3f4a8a4,0x21661852,0x26a11d4d,0x270524dc,0x2c5029f8,0x29ac2897,0x2efc2da6,0x2bd72ac1,0x30d7302a,
0xac50acf5,0xb0d7b192,0xaa11ab59,0xaec9b01d,0xa705a8ca,0xabd7ad5a,0x9fa8a478,0xa445a8fc,0x2262191b,0x271f1db2,0x282625bf,0x2ca22a69,0x2ab5296d,0x2f822e11,0x2ca22bfd,0x3135307a,
0xacfbadb9,0xb12eb1f7,0xab00ac3d,0xaf42b067,0xa80da987,0xac31adb9,0xa06ba528,0xa491a954,0x235d19e4,0x279c1e16,0x28ca26a1,0x2cf52adb,0x2bbe2a43,0x30042e7d,0x2d5a2c9c,0x319230ca,
0xb185b25c,0xb426b4cc,0xafbbb0b1,0xb1c6b306,0xac76ae18,0xaea3b08a,0xa4dca9ac,0xa738ac37,0x280d1e7b,0x2a0520d0,0x2d472b4c,0x2fdb2d6d,0x30472ee9,0x32663128,0x31f0311b,0x347933a8,
0xb1ddb2c1,0xb453b501,0xb01ab0fb,0xb204b352,0xacbcae77,0xaee9b0ba,0xa528aa05,0xa783ac63,0x284c1edf,0x2a432102,0x2d992bbe,0x30172da6,0x308a2f55,0x32aa315f,0x324f316b,0x34aa33fc,
0xb235b327,0xb481b537,0xb057b145,0xb242b39e,0xad01aed6,0xaf2fb0eb,0xa573aa5d,0xa7cfac90,0x288b1f44,0x2a822134,0x2deb2c18,0x30412ddf,0x30ce2fc2,0x32ef3196,0x32ae31bc,0x34db3428,
0xb28db38e,0xb4afb56d,0xb094b18f,0xb280b3eb,0xad47af36,0xaf75b11b,0xa5bfaab5,0xa80dacbc,0x28ca1fa8,0x2ac12166,0x2e3e2c50,0x306a2e18,0x31113017,0x333531cd,0x330d320e,0x350d3452,
0xb2e5b3f5,0xb4ddb5a3,0xb0d1b1da,0xb2beb41c,0xad8caf95,0xafbbb14b,0xa60aab0d,0xa833ace8,0x29092006,0x2b002199,0x2e902c89,0x30942e51,0x3155304d,0x337a3204,0x336d325f,0x3540347c,
0xb33eb42e,0xb50cb5da,0xb10eb224,0xb2fcb443,0xadd2aff5,0xb001b17c,0xa655ab65,0xa859ad14,0x29482039,0x2b4021cb,0x2ee32cc2,0x30be2e8a,0x31993084,0x33c0323b,0x33cd32b1,0x357234a6,
0xb398b463,0xb53ab612,0xb14bb26f,0xb33bb469,0xae18b02a,0xb024b1ac,0xa6a1abbe,0xa87ead40,0x2987206b,0x2b7f21fd,0x2f362cfb,0x30e72ec3,0x31dd30ba,0x34033273,0x34173303,0x35a534d1,
0xb3f2b497,0xb569b64a,0xb189b2bb,0xb37ab490,0xae5eb05a,0xb047b1dd,0xa6ecac0b,0xa8a4ad6d,0x29c6209d,0x2bbe222f,0x2f882d34,0x31112efc,0x322130f1,0x342632aa,0x34483356,0x35d934fc,
0xb599b682,0xb722b82e,0xb3b9b4b7,0xb4ddb5f9,0xb06ab20e,0xb185b398,0xa8caad99,0xa9f8aefc,0x2bfd2262,0x2cfb23f4,0x313b2f36,0x328d3081,0x344932e2,0x35693453,0x360d3527,0x37bd368b,
0xb5c9b6bb,0xb755b84d,0xb3f8b4df,0xb4feb622,0xb08db23e,0xb1a9b3ca,0xa8f0adc5,0xaa1eaf29,0x2c1e2294,0x2d1b2413,0x31652f6f,0x32b7309d,0x346d331a,0x358e3470,0x36413553,0x37f536ba,
0xb5f9b6f5,0xb789b86d,0xb41cb506,0xb51fb64c,0xb0b1b26f,0xb1cdb3fc,0xa915adf2,0xaa43af55,0x2c3d22c6,0x2d3a242c,0x318f2fa8,0x32e230ba,0x34903352,0x35b3348d,0x3676357e,0x381736e8,
0xb629b72f,0xb7bdb88d,0xb43cb52e,0xb540b676,0xb0d4b2a1,0xb1f0b417,0xa93bae1e,0xaa69af82,0x2c5d22f9,0x2d5a2445,0x31b92fe2,0x330d30d7,0x34b4338b,0x35d934aa,0x36ab35ab,0x38343717,
0xb65ab76a,0xb7f1b8ad,0xb45cb556,0xb561b6a0,0xb0f7b2d2,0xb214b430,0xa961ae4b,0xaa8fafaf,0x2c7d232b,0x2d79245f,0x31e3300e,0x333830f4,0x34d833c3,0x35fe34c7,0x36e035d7,0x38513746,
0xb68bb7a5,0xb813b8ce,0xb47cb57e,0xb582b6ca,0xb11bb303,0xb238b449,0xa987ae77,0xaab5afdb,0x2c9c235d,0x2d992478,0x320e302a,0x33633111,0x34fc33fc,0x362434e4,0x37173604,0x386f3775,
0xb6bdb7e2,0xb82eb8f0,0xb49cb5a7,0xb5a3b6f5,0xb13eb335,0xb25cb463,0xa9acaea3,0xaadbb004,0x2cbc238f,0x2db92491,0x32383047,0x338e312e,0x3520341a,0x364a3501,0x374d3631,0x388d37a5,
0xb6efb80f,0xb849b911,0xb4bdb5d0,0xb5c5b720,0xb162b366,0xb280b47c,0xa9d2aed0,0xab00b01a,0x2cdb23c2,0x2dd824aa,0x32623064,0x33b9314b,0x35453437,0x3670351f,0x3785365e,0x38ab37d6,
0xb865b934,0xb94dba5c,0xb5e7b74c,0xb6fcb85a,0xb2a4b495,0xb3c6b564,0xab26b031,0xac2bb0e4,0x2df824c3,0x2ef6258c,0x33e43168,0x34a13252,0x3697353c,0x37d4362d,0x38ca3803,0x39d038d0,
0xb880b957,0xb96bba84,0xb609b777,0xb720b872,0xb2c8b4af,0xb3ebb57e,0xab4cb047,0xac3db0fb,0x2e1824dc,0x2f1625a5,0x34083185,0x34b7326f,0x36bd355a,0x37fd364c,0x38e9381c,0x39f338eb,
0xb89cb97a,0xb98abaad,0xb62bb7a4,0xb744b88a,0xb2ecb4c9,0xb408b599,0xab72b05d,0xac50b111,0x2e3724f5,0x2f3625bf,0x341e31a2,0x34ce328d,0x36e43577,0x3813366b,0x39093835,0x3a173906,
0xb8b9b99e,0xb9aabad7,0xb64db7d0,0xb768b8a2,0xb310b4e2,0xb41ab5b3,0xab98b074,0xac63b128,0x2e57250f,0x2f5525d8,0x343331c0,0x34e432aa,0x370b3595,0x3828368a,0x3929384e,0x3a3b3922,
0xb8d6b9c3,0xb9cabb02,0xb670b7fd,0xb78cb8ba,0xb335b4fc,0xb42db5ce,0xabbeb08a,0xac76b13e,0x2e772528,0x2f7525f1,0x344931dd,0x34fa32c8,0x373335b3,0x383d36a9,0x39493868,0x3a60393e,
0xb8f3b9e8,0xb9ebbb2d,0xb693b815,0xb7b1b8d2,0xb359b516,0xb43fb5e9,0xabe3b0a1,0xac89b155,0x2e972541,0x2f95260a,0x345f31fa,0x351132e5,0x375b35d2,0x385236c8,0x396a3881,0x3a86395a,
0xb910ba0e,0xba0cbb59,0xb6b6b82c,0xb7d6b8eb,0xb37db530,0xb452b604,0xac05b0b7,0xac9cb16b,0x2eb6255a,0x2fb52623,0x34753217,0x35273303,0x378335f0,0x386836e8,0x398c389b,0x3aac3977,
0xb92eba35,0xba2dbb87,0xb6d9b843,0xb7fbb904,0xb3a2b54a,0xb464b61e,0xac18b0ce,0xacafb182,0x2ed62573,0x2fd5263c,0x348b3235,0x353e3321,0x37ab360e,0x387d3708,0x39ae38b6,0x3ad33994,
0x9ce99db2,0xad3aae11,0x9aad9c20,0xab1aac63,0x9712991b,0xa783a96d,0x8a4893db,0x9aada42c,0x157f10b6,0x25d82102,0x19e41852,0x2a432897,0x1c841b76,0x2ccf2bf0,0x1e161d4d,0x2e7d2da6,
0xa35da445,0xadd8aec9,0xa102a22f,0xabf0ace8,0x9d4d9fa8,0xa833aa11,0x90b699e4,0x9b76a4aa,0x1c201712,0x26882199,0x206b1e7b,0x2b002922,0x22c62199,0x2d602c70,0x249123f4,0x2f422e51,
0xa623a71f,0xae77af82,0xa42ca528,0xac63ad6d,0xa06ba262,0xa8a4aab5,0x93db9ce9,0x9c20a528,0x1edf19e4,0x2738222f,0x235d2166,0x2bbe29ac,0x25a524aa,0x2df22ce8,0x279c26a1,0x30042efc,
0xa84ca8fc,0xaf16b01d,0xa5d8a738,0xaccfadf2,0xa22fa478,0xa915ab59,0x957f9edf,0x9c84a5a5,0x20d01c20,0x27e822c6,0x2528238f,0x2c3d2a37,0x27e82688,0x2e842d60,0x295428a4,0x30672fa8,
0xa987aa69,0xafb5b07a,0xa783a8a4,0xad3aae77,0xa3f4a5bf,0xa987abfd,0x9712a06b,0x9ce9a623,0x222f1d4d,0x284c235d,0x26a124dc,0x2c9c2ac1,0x29152833,0x2f162dd8,0x2adb29f8,0x30ca302a,
0xaac1abd7,0xb02ab0d7,0xa897a9ac,0xada6aefc,0xa4dca705,0xa9f8ac50,0x9852a166,0x9d4da6a1,0x238f1e7b,0x28a423f4,0x280d25f1,0x2cfb2b4c,0x2a372922,0x2fa82e51,0x2c312b4c,0x312e3081,
0xabfdaca2,0xb07ab135,0xa96daab5,0xae11af82,0xa5bfa826,0xaa69aca2,0x991ba262,0x9db2a71f,0x24781fa8,0x28fc2445,0x28ca2705,0x2d5a2bd7,0x2b592a11,0x301d2ec9,0x2cf52c50,0x319230d7,
0xac9cad5a,0xb0cab192,0xaa43abbe,0xae7db004,0xa6a1a8ca,0xaadbacf5,0x99e4a35d,0x9e16a79c,0x2528206b,0x29542491,0x2987280d,0x2db92c31,0x2c3d2b00,0x30672f42,0x2db92cfb,0x31f7312e,
0xb11bb1f0,0xb3a8b479,0xaee9b047,0xb128b266,0xab4cad47,0xad6dafdb,0x9e7ba80d,0xa0d0aa05,0x29ac24dc,0x2c372738,0x2e182c76,0x308a2ea3,0x30b12fbb,0x330631c6,0x325c3185,0x34cc3426,
0xb16bb24f,0xb3fcb4aa,0xaf55b08a,0xb15fb2aa,0xabbead99,0xada6b017,0x9edfa84c,0xa102aa43,0x2a052528,0x2c632783,0x2e772cbc,0x30ba2ee9,0x30fb301a,0x33523204,0x32c131dd,0x35013453,
0xb1bcb2ae,0xb428b4db,0xafc2b0ce,0xb196b2ef,0xac18adeb,0xaddfb041,0x9f44a88b,0xa134aa82,0x2a5d2573,0x2c9027cf,0x2ed62d01,0x30eb2f2f,0x31453057,0x339e3242,0x33273235,0x35373481,
0xb20eb30d,0xb452b50d,0xb017b111,0xb1cdb335,0xac50ae3e,0xae18b06a,0x9fa8a8ca,0xa166aac1,0x2ab525bf,0x2cbc280d,0x2f362d47,0x311b2f75,0x318f3094,0x33eb3280,0x338e328d,0x356d34af,
0xb25fb36d,0xb47cb540,0xb04db155,0xb204b37a,0xac89ae90,0xae51b094,0xa006a909,0xa199ab00,0x2b0d260a,0x2ce82833,0x2f952d8c,0x314b2fbb,0x31da30d1,0x341c32be,0x33f532e5,0x35a334dd,
0xb2b1b3cd,0xb4a6b572,0xb084b199,0xb23bb3c0,0xacc2aee3,0xae8ab0be,0xa039a948,0xa1cbab40,0x2b652655,0x2d142859,0x2ff52dd2,0x317c3001,0x3224310e,0x344332fc,0x342e333e,0x35da350c,
0xb303b417,0xb4d1b5a5,0xb0bab1dd,0xb273b403,0xacfbaf36,0xaec3b0e7,0xa06ba987,0xa1fdab7f,0x2bbe26a1,0x2d40287e,0x302a2e18,0x31ac3024,0x326f314b,0x3469333b,0x34633398,0x3612353a,
0xb356b448,0xb4fcb5d9,0xb0f1b221,0xb2aab426,0xad34af88,0xaefcb111,0xa09da9c6,0xa22fabbe,0x2c0b26ec,0x2d6d28a4,0x305a2e5e,0x31dd3047,0x32bb3189,0x3490337a,0x349733f2,0x364a3569,
0xb527b60d,0xb68bb7bd,0xb2e2b449,0xb453b569,0xaf36b13b,0xb081b28d,0xa262abfd,0xa3f4acfb,0x2d9928ca,0x2efc29f8,0x320e306a,0x33983185,0x34b733b9,0x35f934dd,0x36823599,0x382e3722,
0xb553b641,0xb6bab7f5,0xb31ab46d,0xb470b58e,0xaf6fb165,0xb09db2b7,0xa294ac1e,0xa413ad1b,0x2dc528f0,0x2f292a1e,0x323e308d,0x33ca31a9,0x34df33f8,0x362234fe,0x36bb35c9,0x384d3755,
0xb57eb676,0xb6e8b817,0xb352b490,0xb48db5b3,0xafa8b18f,0xb0bab2e2,0xa2c6ac3d,0xa42cad3a,0x2df22915,0x2f552a43,0x326f30b1,0x33fc31cd,0x3506341c,0x364c351f,0x36f535f9,0x386d3789,
0xb5abb6ab,0xb717b834,0xb38bb4b4,0xb4aab5d9,0xafe2b1b9,0xb0d7b30d,0xa2f9ac5d,0xa445ad5a,0x2e1e293b,0x2f822a69,0x32a130d4,0x341731f0,0x352e343c,0x36763540,0x372f3629,0x388d37bd,
0xb5d7b6e0,0xb746b851,0xb3c3b4d8,0xb4c7b5fe,0xb00eb1e3,0xb0f4b338,0xa32bac7d,0xa45fad79,0x2e4b2961,0x2faf2a8f,0x32d230f7,0x34303214,0x3556345c,0x36a03561,0x376a365a,0x38ad37f1,
0xb604b717,0xb775b86f,0xb3fcb4fc,0xb4e4b624,0xb02ab20e,0xb111b363,0xa35dac9c,0xa478ad99,0x2e772987,0x2fdb2ab5,0x3303311b,0x34493238,0x357e347c,0x36ca3582,0x37a5368b,0x38ce3813,
0xb631b74d,0xb7a5b88d,0xb41ab520,0xb501b64a,0xb047b238,0xb12eb38e,0xa38facbc,0xa491adb9,0x2ea329ac,0x30042adb,0x3335313e,0x3463325c,0x35a7349c,0x36f535a3,0x37e236bd,0x38f0382e,
0xb65eb785,0xb7d6b8ab,0xb437b545,0xb51fb670,0xb064b262,0xb14bb3b9,0xa3c2acdb,0xa4aaadd8,0x2ed029d2,0x301a2b00,0x33663162,0x347c3280,0x35d034bd,0x372035c5,0x380f36ef,0x39113849,
0xb803b8ca,0xb8d0b9d0,0xb53cb697,0xb62db7d4,0xb168b3e4,0xb252b4a1,0xa4c3adf8,0xa58caef6,0x30312b26,0x30e42c2b,0x349532a4,0x356433c6,0x374c35e7,0x385a36fc,0x39343865,0x3a5c394d,
0xb81cb8e9,0xb8ebb9f3,0xb55ab6bd,0xb64cb7fd,0xb185b408,0xb26fb4b7,0xa4dcae18,0xa5a5af16,0x30472b4c,0x30fb2c3d,0x34af32c8,0x357e33eb,0x37773609,0x38723720,0x39573880,0x3a84396b,
0xb835b909,0xb906ba17,0xb577b6e4,0xb66bb813,0xb1a2b41e,0xb28db4ce,0xa4f5ae37,0xa5bfaf36,0x305d2b72,0x31112c50,0x34c932ec,0x35993408,0x37a4362b,0x388a3744,0x397a389c,0x3aad398a,
0xb84eb929,0xb922ba3b,0xb595b70b,0xb68ab828,0xb1c0b433,0xb2aab4e4,0xa50fae57,0xa5d8af55,0x30742b98,0x31282c63,0x34e23310,0x35b3341a,0x37d0364d,0x38a23768,0x399e38b9,0x3ad739aa,
0xb868b949,0xb93eba60,0xb5b3b733,0xb6a9b83d,0xb1ddb449,0xb2c8b4fa,0xa528ae77,0xa5f1af75,0x308a2bbe,0x313e2c76,0x34fc3335,0x35ce342d,0x37fd3670,0x38ba378c,0x39c338d6,0x3b0239ca,
0xb881b96a,0xb95aba86,0xb5d2b75b,0xb6c8b852,0xb1fab45f,0xb2e5b511,0xa541ae97,0xa60aaf95,0x30a12be3,0x31552c89,0x35163359,0x35e9343f,0x38153693,0x38d237b1,0x39e838f3,0x3b2d39eb,
0xb89bb98c,0xb977baac,0xb5f0b783,0xb6e8b868,0xb217b475,0xb303b527,0xa55aaeb6,0xa623afb5,0x30b72c05,0x316b2c9c,0x3530337d,0x36043452,0x382c36b6,0x38eb37d6,0x3a0e3910,0x3b593a0c,
0xb8b6b9ae,0xb994bad3,0xb60eb7ab,0xb708b87d,0xb235b48b,0xb321b53e,0xa573aed6,0xa63cafd5,0x30ce2c18,0x31822caf,0x354a33a2,0x361e3464,0x384336d9,0x390437fb,0x3a35392e,0x3b873a2d,
0x214d2216,0x319b326c,0x1f762084,0x2fe830c8,0x1c521de4,0x2c962e40,0x14b6197f,0x250229d7,0x97db8e48,0xa82c9ead,0x9d1b9b12,0xad6bab82,0xa0209ead,0xb05eaf14,0xa1b2a0e9,0xb204b131,
0x27f32890,0x3241332b,0x259826c6,0x306a3156,0x227b246b,0x2d202efb,0x1b122020,0x25982a87,0x9de494b6,0xa8aa9f76,0xa3a8a14d,0xae0eac32,0xa62fa502,0xb0e1afe8,0xa845a75d,0xb2b6b1cc,
0x2aa02b9b,0x32e733e8,0x28aa29a5,0x30e131e5,0x2566275d,0x2daa2fb6,0x1de422df,0x262f2b36,0xa0e997db,0xa927a020,0xa661a46b,0xaeb0aca2,0xa927a82c,0xb163b05e,0xab1daa22,0xb368b266,
0x2ca22d52,0x338d3452,0x2a872be6,0x31563273,0x278f2927,0x2e333039,0x202024cf,0x26c62be6,0xa2df997f,0xa9a5a084,0xa877a62f,0xaf53ad13,0xab36a9d7,0xb1e5b0c8,0xacfaac4b,0xb40cb300,
0x2df52ed6,0x341834b0,0x2c322d13,0x31cc3300,0x28dc2aa0,0x2ebd3096,0x214d262f,0x275d2c4b,0xa46b9b12,0xaa22a0e9,0xa9bea7f3,0xaff5ad84,0xaca2ab82,0xb266b131,0xae65ad84,0xb464b399,
0x2f46302c,0x346a350c,0x2d202e33,0x3241338d,0x29f02c0c,0x2f4630f3,0x227b278f,0x27f32ca2,0xa5669c52,0xaaa0a14d,0xab04a8dc,0xb04badf5,0xadaaac96,0xb2e7b19b,0xafcfaebd,0xb4bcb418,
0x304b30ed,0x34bc3568,0x2e0e2f53,0x32b6340c,0x2b042cc8,0x2fcf3150,0x23a82877,0x28452cfa,0xa6619d1b,0xab1da1b2,0xac25a9be,0xb09cae65,0xaeb0ad6b,0xb368b204,0xb09caff5,0xb512b464,
0x30f331ad,0x350c35c4,0x2efb3039,0x332b3452,0x2c0c2d84,0x302c31ad,0x246b2927,0x28902d52,0xa75d9de4,0xab9ba216,0xacc8aaa0,0xb0edaed6,0xafb6ae40,0xb3e8b26c,0xb150b096,0xb568b4b0,
0x355d361e,0x37c63867,0x339f3497,0x359836b4,0x3071320a,0x32913473,0x28dc2daa,0x2b363032,0xac0ca27b,0xae01a4cf,0xb13eaf46,0xb3bdb163,0xb434b2d5,0xb627b506,0xb5beb4fa,0xb826b73e,
0x35ac3678,0x3808388f,0x340934dd,0x35cf36f5,0x30b53266,0x32d534a0,0x29272e01,0x2b82305e,0xac4ba2df,0xae40a502,0xb18eafb6,0xb406b19b,0xb473b33d,0xb663b539,0xb612b545,0xb84cb784,
0x35fb36d0,0x382c38b7,0x34433521,0x36073736,0x30f932c2,0x331834ce,0x29722e59,0x2bcd308a,0xac89a344,0xae7ea534,0xb1dfb013,0xb42eb1d2,0xb4b3b3a5,0xb6a0b56b,0xb666b58f,0xb872b7c9,
0x36493728,0x385038de,0x347c3565,0x363e3776,0x313e331e,0x335c34fa,0x29be2eb0,0x2c0c30b5,0xacc8a3a8,0xaebda566,0xb22fb04b,0xb455b20a,0xb4f1b406,0xb6dcb59d,0xb6b9b5d8,0xb898b807,
0x3697377e,0x38743904,0x34b635a9,0x367537b6,0x3182337a,0x339f3527,0x2a092f08,0x2c3230e1,0xad07a406,0xaefba598,0xb27fb083,0xb47cb241,0xb530b43a,0xb717b5cf,0xb70cb621,0xb8bdb828,
0x36e437d4,0x3897392a,0x34ee35ed,0x36ab37f5,0x31c633d6,0x33e23554,0x2a542f5f,0x2c57310c,0xad45a439,0xaf3aa5cb,0xb2cfb0bb,0xb4a4b279,0xb56eb46d,0xb752b601,0xb75db669,0xb8e1b84a,
0x37303814,0x38b9394e,0x3527362f,0x36e1381a,0x320a3418,0x34123580,0x2aa02fb6,0x2c7d3137,0xad84a46b,0xaf78a5fd,0xb31eb0f3,0xb4cbb2b0,0xb5acb4a0,0xb78cb632,0xb7adb6b1,0xb905b86b,
0x377c383e,0x38db3972,0x355f3672,0x37173838,0x324e3446,0x343435ac,0x2aeb3007,0x2ca23163,0xadc3a49d,0xafb6a62f,0xb36eb12b,0xb4f1b2e7,0xb5eab4d4,0xb7c6b663,0xb7fdb6f8,0xb928b88b,
0x38fd3996,0x39f33a91,0x374c3857,0x3874393e,0x345535d8,0x355d3730,0x2cc8318e,0x2df532e7,0xaff5a661,0xb0f3a7f3,0xb518b31e,0xb649b46a,0xb800b694,0xb8dbb808,0xb94bb8ab,0xba45b99b,
0x391e39b8,0x3a0f3aad,0x37813875,0x388c3959,0x34763604,0x357d375a,0x2cee31b9,0x2e1a3312,0xb01aa694,0xb112a813,0xb53fb356,0xb66fb485,0xb81cb6c5,0xb8f5b81f,0xb96db8cb,0xba61b9b7,
0x393e39da,0x3a2b3ac7,0x37b63893,0x38a53974,0x3497362f,0x359d3784,0x2d1331e5,0x2e40333d,0xb039a6c6,0xb131a82c,0xb565b38d,0xb694b4a0,0xb838b6f5,0xb90fb836,0xb98eb8ea,0xba7cb9d2,
0x395e39fb,0x3a453ae0,0x37ea38b0,0x38bd398e,0x34b9365b,0x35be37ad,0x2d393210,0x2e653368,0xb058a6f8,0xb150a845,0xb58cb3c3,0xb6b9b4bc,0xb854b725,0xb928b84c,0xb9aeb909,0xba97b9ed,
0x397d3a1b,0x3a5f3af9,0x380f38cd,0x38d539a8,0x34da3686,0x35de37d7,0x2d5e323b,0x2e8b3393,0xb077a72a,0xb16fa85e,0xb5b2b3fa,0xb6deb4d7,0xb870b755,0xb941b863,0xb9ceb927,0xbab0ba07,
0x399b3a3a,0x3a793b10,0x382838ea,0x38ed39c1,0x34fa36b1,0x35fe3800,0x2d843266,0x2eb033bd,0xb096a75d,0xb18ea877,0xb5d8b418,0xb703b4f1,0xb88bb784,0xb95ab879,0xb9edb945,0xbac9ba21,
0x39b93a58,0x3a913b26,0x38423906,0x390439da,0x351b36dc,0x361e3814,0x2daa3291,0x2ed633e8,0xb0b5a78f,0xb1ada890,0xb5feb434,0xb728b50c,0xb8a6b7b3,0xb972b88f,0xba0bb962,0xbae0ba3a,
0x39d73a75,0x3aa93b3c,0x385b3922,0x391b39f2,0x353c3706,0x363e3828,0x2dcf32bc,0x2efb3409,0xb0d4a7c1,0xb1cca8aa,0xb624b44f,0xb74cb527,0xb8c1b7e2,0xb98ab8a5,0xba29b97f,0xbaf7ba52,
0x3ac03b50,0x3b5e3bcb,0x39323a0a,0x39de3ab8,0x365e383c,0x375738d7,0x2f21341f,0x302634c8,0xb1eba8c3,0xb2e1a98c,0xb770b542,0xb846b615,0xb9a2b8bb,0xba51b960,0xbb0dba6a,0xbb9cbb11,
0x3ad73b63,0x3b6e3bd6,0x39493a22,0x39f23acb,0x367d3850,0x377638ea,0x2f463434,0x303934dd,0xb20aa8dc,0xb300a9a5,0xb795b55d,0xb857b62f,0xb9b9b8d0,0xba65b974,0xbb22ba81,0xbba9bb24,
0x3aec3b75,0x3b7d3bdf,0x395f3a39,0x3a063ade,0x369d3864,0x379538fd,0x2f6c3449,0x304b34f1,0xb229a8f5,0xb31ea9be,0xb7b8b577,0xb868b649,0xb9d0b8e5,0xba79b987,0xbb36ba97,0xbbb6bb35,
0x3b013b86,0x3b8c3be7,0x39753a4f,0x3a193af0,0x36bc3878,0x37b3390f,0x2f91345e,0x305e3506,0xb247a90e,0xb33da9d7,0xb7dcb592,0xb879b663,0xb9e7b8fa,0xba8cb99a,0xbb4abaad,0xbbc2bb46,
0x3b153b96,0x3b993bee,0x398a3a65,0x3a2d3b02,0x36dc388b,0x37d13921,0x2fb63473,0x3071351b,0xb266a927,0xb35ca9f0,0xb800b5ac,0xb88ab67d,0xb9fdb90f,0xba9fb9ad,0xbb5cbac3,0xbbccbb56,
0x3b283ba5,0x3ba63bf4,0x39a03a7a,0x3a3f3b13,0x36fb389e,0x37ef3933,0x2fdc3488,0x30833530,0xb285a940,0xb37aaa09,0xb811b5c7,0xb89bb697,0xba12b924,0xbab1b9c0,0xbb6dbad7,0xbbd6bb65,
0x3b3b3bb3,0x3bb23bf9,0x39b53a8f,0x3a523b24,0x371a38b2,0x38073945,0x3001349d,0x30963545,0xb2a4a959,0xb399aa22,0xb823b5e1,0xb8abb6b1,0xba28b938,0xbac3b9d2,0xbb7ebaeb,0xbbdfbb74,
0x3b4d3bc0,0x3bbd3bfc,0x39ca3aa4,0x3a643b34,0x373938c5,0x38153957,0x301334b3,0x30a9355a,0xb2c2a972,0xb3b7aa3b,0xb834b5fb,0xb8bcb6ca,0xba3cb94c,0xbad4b9e4,0xbb8dbaff,0xbbe6bb82,
0x20e921b2,0x31313204,0x1ead2020,0x2f14305e,0x1b121d1b,0x2b822d6b,0xe4817db,0x1ead282c,0x997f94b6,0xa9d7a502,0x9de49c52,0xae40ac96,0xa0849f76,0xb0c8afe8,0xa216a14d,0xb26cb19b,
0x275d2845,0x31cc32b6,0x2502262f,0x2fe830e1,0x214d23a8,0x2c322e0e,0x14b61de4,0x1f7628aa,0xa0209b12,0xaa87a598,0xa46ba27b,0xaefbad20,0xa6c6a598,0xb156b06a,0xa890a7f3,0xb32bb241,
0x2a222b1d,0x32663368,0x282c2927,0x305e3163,0x246b2661,0x2ca22eb0,0x17db20e9,0x20202927,0xa2df9de4,0xab36a62f,0xa75da566,0xafb6adaa,0xa9a5a8aa,0xb1e5b0e1,0xab9baaa0,0xb3e8b2e7,
0x2c4b2cfa,0x3300340c,0x29d72b36,0x30c831e5,0x262f2877,0x2d132f53,0x197f22df,0x208429a5,0xa4cfa020,0xabe6a6c6,0xa927a78f,0xb039ae33,0xabe6aa87,0xb273b156,0xad52aca2,0xb452b38d,
0x2d842e65,0x33993464,0x2b822ca2,0x31313266,0x27f329be,0x2d842ff5,0x1b12246b,0x20e92a22,0xa62fa14d,0xac4ba75d,0xaaa0a8dc,0xb096aebd,0xad13ac32,0xb300b1cc,0xaed6adf5,0xb4b0b418,
0x2ebd2fcf,0x341834bc,0x2c962daa,0x319b32e7,0x28dc2b04,0x2df5304b,0x1c522566,0x214d2aa0,0xa78fa27b,0xaca2a7f3,0xac0ca9f0,0xb0f3af46,0xae33ad20,0xb38db241,0xb02caf46,0xb50cb46a,
0x2ff5309c,0x34643512,0x2d6b2eb0,0x32043368,0x29be2c25,0x2e65309c,0x1d1b2661,0x21b22b1d,0xa877a3a8,0xacfaa845,0xacc8ab04,0xb150afcf,0xaf53ae0e,0xb40cb2b6,0xb0edb04b,0xb568b4bc,
0x30963150,0x34b03568,0x2e402fb6,0x326c33e8,0x2aa02cc8,0x2ed630ed,0x1de4275d,0x22162b9b,0xa927a46b,0xad52a890,0xad84ac0c,0xb1adb02c,0xb039aefb,0xb452b32b,0xb1adb0f3,0xb5c4b50c,
0x34fa35be,0x373e3826,0x32d53434,0x35063627,0x2f46313e,0x316333bd,0x227b2c0c,0x24cf2e01,0xadaaa8dc,0xb032ab36,0xb20ab071,0xb473b291,0xb497b39f,0xb6b4b598,0xb61eb55d,0xb867b7c6,
0x35453612,0x3784384c,0x333d3473,0x35393663,0x2fb6318e,0x319b3406,0x22df2c4b,0x25022e40,0xae01a927,0xb05eab82,0xb266b0b5,0xb4a0b2d5,0xb4ddb409,0xb6f5b5cf,0xb678b5ac,0xb88fb808,
0x358f3666,0x37c93872,0x33a534b3,0x356b36a0,0x301331df,0x31d2342e,0x23442c89,0x25342e7e,0xae59a972,0xb08aabcd,0xb2c2b0f9,0xb4ceb318,0xb521b443,0xb736b607,0xb6d0b5fb,0xb8b7b82c,
0x35d836b9,0x38073898,0x340634f1,0x359d36dc,0x304b322f,0x320a3455,0x23a82cc8,0x25662ebd,0xaeb0a9be,0xb0b5ac0c,0xb31eb13e,0xb4fab35c,0xb565b47c,0xb776b63e,0xb728b649,0xb8deb850,
0x3621370c,0x382838bd,0x343a3530,0x35cf3717,0x3083327f,0x3241347c,0x24062d07,0x25982efb,0xaf08aa09,0xb0e1ac32,0xb37ab182,0xb527b39f,0xb5a9b4b6,0xb7b6b675,0xb77eb697,0xb904b874,
0x3669375d,0x384a38e1,0x346d356e,0x36013752,0x30bb32cf,0x327934a4,0x24392d45,0x25cb2f3a,0xaf5faa54,0xb10cac57,0xb3d6b1c6,0xb554b3e2,0xb5edb4ee,0xb7f5b6ab,0xb7d4b6e4,0xb92ab897,
0x36b137ad,0x386b3905,0x34a035ac,0x3632378c,0x30f3331e,0x32b034cb,0x246b2d84,0x25fd2f78,0xafb6aaa0,0xb137ac7d,0xb418b20a,0xb580b412,0xb62fb527,0xb81ab6e1,0xb814b730,0xb94eb8b9,
0x36f837fd,0x388b3928,0x34d435ea,0x366337c6,0x312b336e,0x32e734f1,0x249d2dc3,0x262f2fb6,0xb007aaeb,0xb163aca2,0xb446b24e,0xb5acb434,0xb672b55f,0xb838b717,0xb83eb77c,0xb972b8db,
0x38ab394b,0x399b3a45,0x36943800,0x380838db,0x331e3518,0x346a3649,0x26612ff5,0x27f330f3,0xb18eacc8,0xb2e7adf5,0xb5d8b455,0xb730b55d,0xb857b74c,0xb93eb874,0xb996b8fd,0xba91b9f3,
0x38cb396d,0x39b73a61,0x36c5381c,0x381f38f5,0x3356353f,0x3485366f,0x2694301a,0x28133112,0xb1b9acee,0xb312ae1a,0xb604b476,0xb75ab57d,0xb875b781,0xb959b88c,0xb9b8b91e,0xbaadba0f,
0x38ea398e,0x39d23a7c,0x36f53838,0x3836390f,0x338d3565,0x34a03694,0x26c63039,0x282c3131,0xb1e5ad13,0xb33dae40,0xb62fb497,0xb784b59d,0xb893b7b6,0xb974b8a5,0xb9dab93e,0xbac7ba2b,
0x390939ae,0x39ed3a97,0x37253854,0x384c3928,0x33c3358c,0x34bc36b9,0x26f83058,0x28453150,0xb210ad39,0xb368ae65,0xb65bb4b9,0xb7adb5be,0xb8b0b7ea,0xb98eb8bd,0xb9fbb95e,0xbae0ba45,
0x392739ce,0x3a073ab0,0x37553870,0x38633941,0x33fa35b2,0x34d736de,0x272a3077,0x285e316f,0xb23bad5e,0xb393ae8b,0xb686b4da,0xb7d7b5de,0xb8cdb80f,0xb9a8b8d5,0xba1bb97d,0xbaf9ba5f,
0x394539ed,0x3a213ac9,0x3784388b,0x3879395a,0x341835d8,0x34f13703,0x275d3096,0x2877318e,0xb266ad84,0xb3bdaeb0,0xb6b1b4fa,0xb800b5fe,0xb8eab828,0xb9c1b8ed,0xba3ab99b,0xbb10ba79,
0x39623a0b,0x3a3a3ae0,0x37b338a6,0x388f3972,0x343435fe,0x350c3728,0x278f30b5,0x289031ad,0xb291adaa,0xb3e8aed6,0xb6dcb51b,0xb814b61e,0xb906b842,0xb9dab904,0xba58b9b9,0xbb26ba91,
0x397f3a29,0x3a523af7,0x37e238c1,0x38a5398a,0x344f3624,0x3527374c,0x27c130d4,0x28aa31cc,0xb2bcadcf,0xb409aefb,0xb706b53c,0xb828b63e,0xb922b85b,0xb9f2b91b,0xba75b9d7,0xbb3cbaa9,
0x3a6a3b0d,0x3b113b9c,0x38bb39a2,0x39603a51,0x35423770,0x36153846,0x28c331eb,0x298c32e1,0xb41faf21,0xb4c8b026,0xb83cb65e,0xb8d7b757,0xba0ab932,0xbab8b9de,0xbb50bac0,0xbbcbbb5e,
0x3a813b22,0x3b243ba9,0x38d039b9,0x39743a65,0x355d3795,0x362f3857,0x28dc320a,0x29a53300,0xb434af46,0xb4ddb039,0xb850b67d,0xb8eab776,0xba22b949,0xbacbb9f2,0xbb63bad7,0xbbd6bb6e,
0x3a973b36,0x3b353bb6,0x38e539d0,0x39873a79,0x357737b8,0x36493868,0x28f53229,0x29be331e,0xb449af6c,0xb4f1b04b,0xb864b69d,0xb8fdb795,0xba39b95f,0xbadeba06,0xbb75baec,0xbbdfbb7d,
0x3aad3b4a,0x3b463bc2,0x38fa39e7,0x399a3a8c,0x359237dc,0x36633879,0x290e3247,0x29d7333d,0xb45eaf91,0xb506b05e,0xb878b6bc,0xb90fb7b3,0xba4fb975,0xbaf0ba19,0xbb86bb01,0xbbe7bb8c,
0x3ac33b5c,0x3b563bcc,0x390f39fd,0x39ad3a9f,0x35ac3800,0x367d388a,0x29273266,0x29f0335c,0xb473afb6,0xb51bb071,0xb88bb6dc,0xb921b7d1,0xba65b98a,0xbb02ba2d,0xbb96bb15,0xbbeebb99,
0x3ad73b6d,0x3b653bd6,0x39243a12,0x39c03ab1,0x35c73811,0x3697389b,0x29403285,0x2a09337a,0xb488afdc,0xb530b083,0xb89eb6fb,0xb933b7ef,0xba7ab9a0,0xbb13ba3f,0xbba5bb28,0xbbf4bba6,
0x3aeb3b7e,0x3b743bdf,0x39383a28,0x39d23ac3,0x35e13823,0x36b138ab,0x295932a4,0x2a223399,0xb49db001,0xb545b096,0xb8b2b71a,0xb945b807,0xba8fb9b5,0xbb24ba52,0xbbb3bb3b,0xbbf9bbb2,
0x3aff3b8d,0x3b823be6,0x394c3a3c,0x39e43ad4,0x35fb3834,0x36ca38bc,0x297232c2,0x2a3b33b7,0xb4b3b013,0xb55ab0a9,0xb8c5b739,0xb957b815,0xbaa4b9ca,0xbb34ba64,0xbbc0bb4d,0xbbfcbbbd,
0x39b839ba,0x3a973ab5,0x39b339b5,0x3a583a78,0x39af39b1,0x3a153a37,0x39aa39ad,0x39cd39f2,0x39a639a8,0x398239a8,0x39a139a4,0x3933395b,0x399d399f,0x38e03909,0x3999399b,0x388938b5,
0xb979b972,0xb865b832,0xb986b980,0xb8c7b896,0xb994b98d,0xb924b8f6,0xb9a1b99b,0xb97db951,0xb9afb9a8,0xb9d2b9a8,0xb9bcb9b5,0xba21b9fa,0xb9c9b9c3,0xba6bba47,0xb9d6b9d0,0xbab0ba8e,
0xb9f4b9fe,0xbac7bae9,0xb9dfb9e9,0xba7ebaa3,0xb9c9b9d4,0xba2dba56,0xb9b3b9be,0xb9d6ba02,0xb99db9a8,0xb979b9a8,0xb986b992,0xb916b948,0xb970b97b,0xb8adb8e2,0xb958b964,0xb840b877,
0x39373927,0x381a37b7,0x39583948,0x38943858,0x39793969,0x390738ce,0x39993989,0x3974393e,0x39b839a8,0x39da39a8,0x39d639c7,0x3a393a0b,0x39f439e5,0x3a903a65,0x3a113a02,0x3ade3ab8,
0x3a2d3a3f,0x3af43b1a,0x3a093a1b,0x3aa23acc,0x39e339f6,0x3a453a74,0x39bc39d0,0x39df3a13,0x399439a8,0x397039a8,0x396b3980,0x38f83935,0x39413956,0x387a38ba,0x3916392b,0x37e83838,
0xb8f3b8d8,0xb79bb705,0xb929b90e,0xb85fb817,0xb95db943,0xb8eab8a6,0xb990b976,0xb96bb92b,0xb9c0b9a8,0xb9e3b9a8,0xb9f0b9d8,0xba50ba1b,0xba1dba07,0xbab3ba83,0xba49ba33,0xbb0abae0,
0xba64ba7c,0xbb1ebb46,0xba31ba4b,0xbac4baf3,0xb9fcba17,0xba5cba92,0xb9c5b9e1,0xb9e7ba23,0xb98bb9a8,0xb966b9a8,0xb94fb96d,0xb8dbb922,0xb911b930,0xb845b891,0xb8d1b8f1,0xb74eb7ee,
0x38ad3887,0x36ff364e,0x38f838d3,0x382a37ac,0x3941391d,0x38cc387c,0x39863964,0x39623918,0x39c939a8,0x39eb39a8,0x3a0939e9,0x3a673a2b,0x3a453a27,0x3ad53aa0,0x3a7e3a62,0x3b323b05,
0x3b453b6e,0x3bbc3bdd,0x3ae53b17,0x3b573b8f,0x3a733aae,0x3ac73b14,0x39f03a33,0x3a113a71,0x395d39a8,0x393739a8,0x38bc390e,0x384038bf,0x380f3867,0x365f3775,0x36af376a,0x341a3540,
0xb65fb593,0xb389b115,0xb7e8b726,0xb625b4f9,0xb8adb852,0xb830b748,0xb958b905,0xb933b8b5,0xb9f4b9a8,0xba15b9a8,0xba7eba3b,0xbad1ba78,0xbaf4babc,0xbb63bb20,0xbb57bb28,0xbbc6bb9b,
0xbb68bb91,0xbbd0bbed,0xbb04bb39,0xbb6fbba6,0xba89bac9,0xbadbbb2b,0xb9f8ba43,0xba19ba7f,0xb954b9a8,0xb92eb9a8,0xb89eb8fb,0xb820b8ab,0xb7b2b83d,0xb5ebb71b,0xb60eb6e3,0xb2deb4b1,
0x35bc34d5,0x32322f0e,0x377a369e,0x35b13469,0x388e3828,0x380f36ee,0x394f38f1,0x392938a0,0x39fc39a8,0x3a1d39a8,0x3a933a4b,0x3ae53a87,0x3b133ad6,0x3b7a3b36,0x3b783b49,0x3bd93bb1,
0x3b873baf,0x3be13bf8,0x3b213b58,0x3b853bbb,0x3a9e3ae3,0x3aee3b41,0x3a003a52,0x3a213a8e,0x394a39a8,0x392439a8,0x387f38e7,0x37fe3896,0x37423812,0x357636c1,0x356a3659,0x31853420,
0xb517b414,0xb0d7abd9,0xb70ab614,0xb53ab3ae,0xb86fb7f9,0xb7ddb693,0xb946b8dd,0xb91fb88c,0xba04b9a8,0xba25b9a8,0xbaa9ba5a,0xbaf7ba95,0xbb2fbaf0,0xbb90bb4b,0xbb96bb67,0xbbe8bbc4,
0xbba3bbc9,0xbbefbbff,0xbb3dbb74,0xbb9abbcd,0xbab3bafc,0xbb01bb55,0xba09ba62,0xba29ba9c,0xb941b9a8,0xb91bb9a8,0xb85fb8d3,0xb7bdb881,0xb6d2b7cd,0xb4ffb665,0xb4c3b5ce,0xb029b31b,
0x346f32a1,0x2ef52248,0x36993587,0x34c33288,0x385037a1,0x379b3637,0x393c38c9,0x39163877,0x3a0d39a8,0x3a2d39a8,0x3abd3a69,0x3b0a3aa3,0x3b4a3b08,0x3ba33b5f,0x3bb03b82,0x3bf43bd5,
0x3bf83c00,0x3bf93bd4,0x3bac3bdc,0x3be43bfe,0x3b133b69,0x3b543bab,0x3a313aaa,0x3a503ae0,0x391139a8,0x38ea39a8,0x377a386d,0x366b3817,0x34873608,0x313b348d,0x2d9731f4,0xad65291b,
0xac3828b6,0x2ec33365,0xb44bb160,0xb0bea57f,0xb759b5da,0xb648b45d,0xb90cb862,0xb8e5b80d,0xba35b9a8,0xba54b9a8,0xbb1bbab1,0xbb5cbae6,0xbbb5bb72,0xbbe9bbb2,0xbbfcbbe3,0xbbf5bc00,
0xbbfebbfc,0xbbefbbbc,0xbbbdbbe9,0xbbeebc00,0xbb24bb7b,0xbb63bbb9,0xba39bab8,0xba58baed,0xb907b9a8,0xb8e0b9a8,0xb737b858,0xb625b802,0xb40eb5ab,0xb042b42c,0xa9b1b0cb,0x30109a48,
0x25e4ad7e,0xb0beb475,0x33a23036,0x2f8ba3db,0x3715357c,0x360233f7,0x3902384d,0x38db37ee,0x3a3d39a8,0x3a5c39a8,0x3b2c3abf,0x3b6a3af3,0x3bc53b84,0x3bf23bc0,0x3bff3bee,0x3be93c00,
0x3c003bf4,0x3be23ba0,0x3bcc3bf3,0x3bf53bff,0x3b353b8c,0x3b713bc6,0x3a413ac6,0x3a603af9,0x38fd39a8,0x38d639a8,0x36f43842,0x35df37d8,0x3328354c,0x2e913396,0x16482f40,0xb16ca852,
0x251b304e,0x32193534,0xb2adae14,0xad972aac,0xb6d2b51d,0xb5bcb334,0xb8f8b838,0xb8d1b7c2,0xba45b9a8,0xba64b9a8,0xbb3dbacc,0xbb78baff,0xbbd3bb95,0xbbf8bbcb,0xbc00bbf7,0xbbdabbfd,
0xbbfebbe6,0xbbd2bb80,0xbbd9bbfa,0xbbfbbbfb,0xbb45bb9d,0xbb7fbbd1,0xba49bad3,0xba67bb05,0xb8f3b9a8,0xb8ccb9a8,0xb6afb82d,0xb599b7ac,0xb232b4ed,0xac9cb2d2,0x294dace7,0x32c62c83,
0xac06b1db,0xb371b5f1,0x31b62b75,0x2b43adb0,0x368d34bd,0x3576326f,0x38ee3822,0x38c73796,0x3a4d39a8,0x3a6b39a8,0x3b4c3ad9,0x3b853b0b,0x3bdf3ba4,0x3bfd3bd6,0x3bfc3bfd,0x3bc83bf8,
0x3bbd3b5a,0x3b473a99,0x3bfe3bf4,0x3bf93bbe,0x3b8b3bdb,0x3bb83bf7,0x3a6f3b11,0x3a8c3b3e,0x38c139a8,0x389939a8,0x35523780,0x343236cc,0x294d320d,0xad332de2,0xb40eaedc,0xb6a4b408,
0x346336aa,0x36f438b0,0xa6ad3004,0x2e2d3451,0xb52fb1aa,0xb40ead1a,0xb8bcb76a,0xb894b6b5,0xba73b9a8,0xba90b9a8,0xbb92bb17,0xbbbdbb43,0xbbffbbe0,0xbbf6bbf9,0xbbb2bbf0,0xbb35bbb4,
0xbba5bb30,0xbb21ba5e,0xbc00bbeb,0xbbf3bbaa,0xbb98bbe4,0xbbc2bbfb,0xba76bb1d,0xba93bb49,0xb8b7b9a8,0xb88eb9a8,0xb50bb753,0xb3d3b69e,0xa17fb147,0x2f27ac51,0x34b73099,0x37423499,
0xb50bb75e,0xb790b900,0x9cb6b12e,0xb010b4e1,0x34e730e4,0x33892b11,0x38b2373d,0x38893687,0x3a7a39a8,0x3a9739a8,0x3b9e3b22,0x3bc63b4e,0x3c003be8,0x3bef3bfd,0x3b983be5,0x3b0d3b9e,
0x3b893b02,0x3af73a1f,0x3c003bdf,0x3beb3b93,0x3ba33bec,0x3bcb3bfe,0x3a7e3b28,0x3a9b3b53,0x38ad39a8,0x388439a8,0x34c33726,0x33403670,0xa51b3080,0xb08d297f,0xb55eb1c3,0xb7ddb529,
0x35b13807,0x3815394d,0x28843257,0x31093570,0xb49fb01d,0xb2f7a7da,0xb8a8b710,0xb87fb659,0xba81b9a8,0xba9eb9a8,0xbba9bb2e,0xbbcfbb58,0xbbffbbef,0xbbe6bbff,0xbb7abbd7,0xbae1bb86,
0xbb6abad0,0xbacbb9dc,0xbbfdbbd0,0xbbe1bb79,0xbbaebbf2,0xbbd3bc00,0xba85bb33,0xbaa2bb5d,0xb8a3b9a8,0xb87ab9a8,0xb47bb6f9,0xb2adb642,0x2a7aaf72,0x3185a4b6,0x360232ea,0x383a35b6,
0xb654b85d,0xb85fb996,0xac38b37d,0xb201b5fd,0x34572eaa,0x32631e48,0x389e36e3,0x3874362b,0x3a8939a8,0x3aa539a8,0x3bb33b39,0x3bd73b62,0x3bfc3bf5,0x3bdc3c00,0x3b593bc7,0x3ab33b6b,
0x39b739b9,0x3a883aa6,0x39b239b4,0x3a483a68,0x39ae39b0,0x3a033a26,0x39a939ab,0x39bb39e0,0x39a539a7,0x396e3995,0x39a039a3,0x391e3947,0x399c399e,0x38ca38f5,0x3997399a,0x3873389f,
0xb97cb975,0xb87eb84c,0xb98ab983,0xb8deb8ae,0xb997b991,0xb93bb90d,0xb9a5b99e,0xb993b967,0xb9b2b9ab,0xb9e6b9bd,0xb9bfb9b9,0xba34ba0e,0xb9ccb9c6,0xba7dba59,0xb9d9b9d3,0xbac0ba9f,
0xb9efb9f9,0xbab6bad9,0xb9d9b9e4,0xba6aba91,0xb9c4b9cf,0xba18ba42,0xb9aeb9b9,0xb9bfb9ec,0xb997b9a3,0xb961b991,0xb981b98c,0xb8fcb92f,0xb96ab975,0xb892b8c8,0xb953b95e,0xb824b85c,
0x3940392f,0x383937f6,0x39613950,0x38b13876,0x39813971,0x392338eb,0x39a03991,0x398e395a,0x39bf39b0,0x39f339c1,0x39de39cf,0x3a4f3a22,0x39fb39ec,0x3aa43a7b,0x3a183a0a,0x3af03acb,
0x3a243a36,0x3ae13b07,0x39ff3a12,0x3a8b3ab7,0x39d939ec,0x3a2c3a5d,0x39b239c6,0x39c439f9,0x398a399e,0x3953398c,0x39613975,0x38d93917,0x3936394b,0x3859389a,0x390b3921,0x37a43816,
0xb901b8e6,0xb7e6b750,0xb936b91c,0xb883b83c,0xb96ab950,0xb90bb8c8,0xb99cb983,0xb98ab94b,0xb9ccb9b4,0xb9ffb9c6,0xb9fbb9e4,0xba6aba36,0xba28ba12,0xbacaba9b,0xba53ba3e,0xbb1dbaf5,
0xba57ba70,0xbb09bb33,0xba24ba3e,0xbaabbadc,0xb9efba0a,0xba40ba77,0xb9b7b9d3,0xb9c8ba05,0xb97cb99a,0xb944b988,0xb940b95e,0xb8b6b8fe,0xb901b921,0xb81eb86b,0xb8c0b8e1,0xb6fcb79e,
0x38c0389a,0x375636a7,0x390b38e6,0x38543800,0x3953392f,0x38f238a4,0x39973975,0x3985393d,0x39d939b9,0x3a0c39ca,0x3a1839f9,0x3a843a4a,0x3a533a36,0x3aed3abb,0x3a8b3a70,0x3b473b1c,
0x3b2e3b5a,0x3ba63bce,0x3aca3afe,0x3b373b74,0x3a533a91,0x3a9d3aef,0x39cc3a12,0x39de3a42,0x39363983,0x38fc3971,0x389238e6,0x37fb3880,0x37c5383c,0x35d136eb,0x3651370d,0x330934ae,
0xb6c3b5fa,0xb460b251,0xb824b788,0xb6b8b590,0xb8d9b880,0xb873b7d5,0xb981b92f,0xb96eb8f5,0xba18b9cf,0xba48b9e0,0xba9dba5d,0xbafabaa6,0xbb0fbad9,0xbb80bb43,0xbb6cbb40,0xbbd8bbb2,
0xbb51bb7d,0xbbbdbbe0,0xbae7bb1f,0xbb4ebb8c,0xba66baa9,0xbaafbb04,0xb9d1ba1e,0xb9e2ba4e,0xb928b97e,0xb8edb96c,0xb86eb8cd,0xb7afb866,0xb74bb80b,0xb54fb684,0xb5a2b679,0xb197b411,
0x362e3549,0x338330de,0x37e6370d,0x3651350e,0x38c0385c,0x38593788,0x397c3921,0x396a38e6,0x3a2439d3,0x3a5339e4,0x3ab63a70,0x3b0f3ab7,0x3b2e3af5,0x3b973b5a,0x3b8d3b61,0x3be83bc7,
0x3b703b9c,0x3bd03bef,0x3b033b3d,0x3b653ba2,0x3a793ac1,0x3ac03b19,0x39d53a2a,0x39e63a59,0x3919397a,0x38de3967,0x384938b4,0x3761384c,0x36cf37b4,0x34cc361d,0x34f035e2,0x302332e4,
0xb596b496,0xb244aecf,0xb783b690,0xb5e8b48a,0xb8a7b836,0xb83eb73a,0xb978b912,0xb965b8d7,0xba30b9d7,0xba5fb9e8,0xbacdba82,0xbb23bac8,0xbb4cbb10,0xbbacbb6f,0xbbaabb7f,0xbbf4bbd8,
0xbb8dbbb7,0xbbe0bbf9,0xbb1dbb5a,0xbb7abbb5,0xba8bbad9,0xbad0bb2d,0xb9d9ba36,0xb9eaba65,0xb90bb975,0xb8cfb963,0xb824b89a,0xb713b831,0xb651b750,0xb447b5b3,0xb43bb549,0xad58b1a4,
0x34fc33c0,0x31032bc0,0x371e3611,0x357e3405,0x388d3811,0x382436eb,0x39733903,0x396138c8,0x3a3c39db,0x3a6a39ec,0x3ae43a94,0x3b373ad9,0x3b673b2a,0x3bbe3b83,0x3bc33b9a,0x3bfc3be7,
0x3bed3bff,0x3bff3bea,0x3b8d3bc7,0x3bcc3bf5,0x3ae13b40,0x3b1d3b83,0x39ef3a70,0x39ff3a9b,0x38c0395e,0x3883394b,0x36c33816,0x357e3750,0x33833549,0x2e84332e,0x28cf3061,0xb0aca5b2,
0xaf7ea376,0x29663166,0xb514b2fd,0xb2bfad71,0xb809b69b,0xb734b555,0xb95cb8b9,0xb949b87b,0xba75b9f1,0xbaa1ba01,0xbb49bae9,0xbb8bbb25,0xbbcfbb96,0xbbf9bbd2,0xbc00bbf2,0xbbe3bbfe,
0xbbf6bc00,0xbbfcbbda,0xbb9fbbd6,0xbbd8bbfb,0xbaf0bb52,0xbb2cbb92,0xb9f3ba7b,0xba03baa6,0xb8b1b95a,0xb873b947,0xb673b7f6,0xb52cb718,0xb276b4de,0xac5eb251,0x2052ae39,0x321f2bf2,
0x2cf4a806,0xad3fb2d8,0x34a831ee,0x31e22a93,0x37db364b,0x36fc3502,0x395738a9,0x3944386b,0x3a8039f5,0x3aab3a05,0x3b5b3af8,0x3b993b33,0x3bdd3ba7,0x3bfd3bdd,0x3bff3bfa,0x3bd13bf9,
0x3bfd3bfd,0x3bf53bc6,0x3baf3be3,0x3be23bff,0x3b003b64,0x3b393ba0,0x39f73a86,0x3a083ab0,0x38a23955,0x38633942,0x362237bf,0x34d836e0,0x31663472,0x286b3172,0xaaf82b5c,0xb390ae84,
0xa8cf2cf4,0x2fc93423,0xb43bb0de,0xb103a484,0xb7a4b5fa,0xb6c3b4ae,0xb953b89a,0xb940b85c,0xba8bb9f9,0xbab6ba0a,0xbb6cbb07,0xbba6bb40,0xbbe8bbb7,0xbc00bbe7,0xbbfabbff,0xbbbabbf1,
0xbc00bbf6,0xbbebbbae,0xbbbebbed,0xbbebbc00,0xbb0fbb74,0xbb47bbad,0xb9fbba91,0xba0cbabb,0xb892b950,0xb854b93d,0xb5d1b788,0xb484b6a7,0xb055b405,0x9248b093,0x2e6ba484,0x347e3086,
0x98b6afe2,0xb128b4d8,0x339c2f97,0x3023a420,0x376c35a8,0x368a345a,0x394e388b,0x393b384c,0x3a9639fd,0x3ac03a0e,0x3b7c3b16,0x3bb33b4d,0x3bf23bc5,0x3c003bef,0x3bf03c00,0x3ba03be5,
0x3bde3b91,0x3b8a3af7,0x3bf23bff,0x3c003be3,0x3b533bb9,0x3b823bdf,0x3a103ac5,0x3a203aec,0x38443939,0x38033925,0x342f366d,0x31b03584,0xa8392f65,0xb15a1d7f,0xb531b1c9,0xb7e0b55b,
0x3269358a,0x35a83819,0xae842a61,0x205231e2,0xb651b405,0xb567b15a,0xb936b83c,0xb923b7f6,0xbacaba12,0xbaf0ba22,0xbbbebb5a,0xbbe3bb88,0xbbfdbbf5,0xbbddbc00,0xbb81bbd6,0xbadfbb7c,
0xbbcebb70,0xbb6dbac6,0xbbf8bbfb,0xbbffbbd6,0xbb60bbc4,0xbb8dbbe7,0xba14bacf,0xba24baf5,0xb834b934,0xb7e6b921,0xb3b4b634,0xb103b549,0x2c44ada3,0x326925b2,0x35e23309,0x384135f4,
0xb3a8b63a,0xb63fb869,0x2cc2ad58,0xa89db2f0,0x3617335f,0x352c30ac,0x3931382c,0x391e37d5,0x3ad43a16,0x3afa3a26,0x3bc93b66,0x3bea3b92,0x3bf93bfa,0x3bcf3bff,0x3b5f3bc5,0x3aad3b5d,
0x3bba3b4c,0x3b4d3a93,0x3bfc3bf6,0x3bfd3bc7,0x3b6c3bce,0x3b973bed,0x3a183ad9,0x3a283afe,0x3824392f,0x37c5391c,0x330935fa,0x3055350e,0xae6b2bc0,0xb377aa61,0xb690b423,0xb890b68a,
0x347236e5,0x36d438b6,0xa9fd2f7e,0x2c1233fd,0xb5dcb2b3,0xb4f0affb,0xb92db81c,0xb919b7b4,0xbaddba1a,0xbb03ba2a,0xbbd3bb72,0xbbf0bb9c,0xbbf2bbfe,0xbbbfbbfc,0xbb38bbaf,0xba77bb3c,
0xbba4bb23,0xbb2aba5b,0xbbffbbee,0xbbfabbb6,0xbb77bbd7,0xbba1bbf3,0xba1cbae2,0xba2cbb07,0xb813b92a,0xb7a4b917,0xb25db5bf,0xaf4cb4d2,0x3048a839,0x34412cf4,0x373a34c0,0x38dc371e,
0xb50eb78e,0xb767b901,0x24e9b0d1,0xadd5b484,0x35a23207,0x34b42e9d,0x3928380b,0x39143793,0x3ae73a1e,0x3b0c3a2e,0x3bdb3b7d,0x3bf53ba6,0x3be93c00,0x3bad3bf7,0x3b0d3b97,0x3a3e3b18,
0xb999b996,0xb889b85d,0xb99db99b,0xb8e0b8b5,0xb9a1b99f,0xb933b909,0xb9a6b9a4,0xb982b95b,0xb9aab9a8,0xb9cdb9a8,0xb9afb9ad,0xba15b9f2,0xb9b3b9b1,0xba58ba37,0xb9b8b9b5,0xba97ba78,
0xb9d6b9dc,0xbab0bad0,0xb9c9b9d0,0xba6bba8e,0xb9bcb9c3,0xba21ba47,0xb9afb9b5,0xb9d2b9fa,0xb9a1b9a8,0xb97db9a8,0xb994b99b,0xb924b951,0xb986b98d,0xb8c7b8f6,0xb979b980,0xb865b896,
0x3958394d,0x38403807,0x39703964,0x38ad3877,0x3986397b,0x391638e2,0x399d3992,0x39793948,0x39b339a8,0x39d639a8,0x39c939be,0x3a2d3a02,0x39df39d4,0x3a7e3a56,0x39f439e9,0x3ac73aa3,
0x3a113a1f,0x3ade3b02,0x39f43a02,0x3a903ab8,0x39d639e5,0x3a393a65,0x39b839c7,0x39da3a0b,0x399939a8,0x397439a8,0x39793989,0x3907393e,0x39583969,0x389438ce,0x39373948,0x381a3858,
0xb916b900,0xb7e8b75e,0xb941b92b,0xb87ab838,0xb96bb956,0xb8f8b8ba,0xb994b980,0xb970b935,0xb9bcb9a8,0xb9dfb9a8,0xb9e3b9d0,0xba45ba13,0xba09b9f6,0xbaa2ba74,0xba2dba1b,0xbaf4bacc,
0xba49ba5e,0xbb0abb30,0xba1dba33,0xbab3bae0,0xb9f0ba07,0xba50ba83,0xb9c0b9d8,0xb9e3ba1b,0xb990b9a8,0xb96bb9a8,0xb95db976,0xb8eab92b,0xb929b943,0xb85fb8a6,0xb8f3b90e,0xb79bb817,
0x38d138b0,0x374e36aa,0x391138f1,0x384537ee,0x394f3930,0x38db3891,0x398b396d,0x39663922,0x39c539a8,0x39e739a8,0x39fc39e1,0x3a5c3a23,0x3a313a17,0x3ac43a92,0x3a643a4b,0x3b1e3af3,
0x3a7e3a99,0x3b323b5a,0x3a453a62,0x3ad53b05,0x3a093a27,0x3a673aa0,0x39c939e9,0x39eb3a2b,0x398639a8,0x396239a8,0x39413964,0x38cc3918,0x38f8391d,0x382a387c,0x38ad38d3,0x36ff37ac,
0xb6afb5f1,0xb41ab1db,0xb80fb76a,0xb65fb540,0xb8bcb867,0xb840b775,0xb95db90e,0xb937b8bf,0xb9f0b9a8,0xba11b9a8,0xba73ba33,0xbac7ba71,0xbae5baae,0xbb57bb14,0xbb45bb17,0xbbbcbb8f,
0xbb57bb80,0xbbc6bbe6,0xbaf4bb28,0xbb63bb9b,0xba7ebabc,0xbad1bb20,0xb9f4ba3b,0xba15ba78,0xb958b9a8,0xb933b9a8,0xb8adb905,0xb830b8b5,0xb7e8b852,0xb625b748,0xb65fb726,0xb389b4f9,
0x360e3534,0x32de304e,0x37b236e3,0x35eb34b1,0x389e383d,0x3820371b,0x395438fb,0x392e38ab,0x39f839a8,0x3a1939a8,0x3a893a43,0x3adb3a7f,0x3b043ac9,0x3b6f3b2b,0x3b683b39,0x3bd03ba6,
0x3b783ba0,0x3bd93bf4,0x3b133b49,0x3b7a3bb1,0x3a933ad6,0x3ae53b36,0x39fc3a4b,0x3a1d3a87,0x394f39a8,0x392939a8,0x388e38f1,0x380f38a0,0x377a3828,0x35b136ee,0x35bc369e,0x32323469,
0xb56ab475,0xb185ad7e,0xb742b659,0xb576b420,0xb87fb812,0xb7feb6c1,0xb94ab8e7,0xb924b896,0xba00b9a8,0xba21b9a8,0xba9eba52,0xbaeeba8e,0xbb21bae3,0xbb85bb41,0xbb87bb58,0xbbe1bbbb,
0xbb96bbbc,0xbbe8bbfc,0xbb2fbb67,0xbb90bbc4,0xbaa9baf0,0xbaf7bb4b,0xba04ba5a,0xba25ba95,0xb946b9a8,0xb91fb9a8,0xb86fb8dd,0xb7ddb88c,0xb70ab7f9,0xb53ab693,0xb517b614,0xb0d7b3ae,
0x34c33365,0x302928b6,0x36d235ce,0x34ff331b,0x385f37cd,0x37bd3665,0x394138d3,0x391b3881,0x3a0939a8,0x3a2939a8,0x3ab33a62,0x3b013a9c,0x3b3d3afc,0x3b9a3b55,0x3ba33b74,0x3bef3bcd,
0x3bb03bd4,0x3bf43c00,0x3b4a3b82,0x3ba33bd5,0x3abd3b08,0x3b0a3b5f,0x3a0d3a69,0x3a2d3aa3,0x393c39a8,0x391639a8,0x385038c9,0x379b3877,0x369937a1,0x34c33637,0x346f3587,0x2ef53288,
0xad972248,0x2d6532a1,0xb487b1f4,0xb13ba91b,0xb77ab608,0xb66bb48d,0xb911b86d,0xb8eab817,0xba31b9a8,0xba50b9a8,0xbb13baaa,0xbb54bae0,0xbbacbb69,0xbbe4bbab,0xbbf8bbdc,0xbbf9bbfe,
0xbbfcbbff,0xbbf5bbc9,0xbbb5bbe3,0xbbe9bc00,0xbb1bbb72,0xbb5cbbb2,0xba35bab1,0xba54bae6,0xb90cb9a8,0xb8e5b9a8,0xb759b862,0xb648b80d,0xb44bb5da,0xb0beb45d,0xac38b160,0x2ec3a57f,
0x29b1abd9,0xb010b414,0x340e30cb,0x30421a48,0x373735ab,0x3625342c,0x39073858,0x38e03802,0x3a3939a8,0x3a5839a8,0x3b243ab8,0x3b633aed,0x3bbd3b7b,0x3bee3bb9,0x3bfe3be9,0x3bef3c00,
0x3bff3bf8,0x3be93baf,0x3bc53bee,0x3bf23c00,0x3b2c3b84,0x3b6a3bc0,0x3a3d3abf,0x3a5c3af3,0x390239a8,0x38db39a8,0x3715384d,0x360237ee,0x33a2357c,0x2f8b33f7,0x25e43036,0xb0bea3db,
0x96482f0e,0x316c34d5,0xb328af40,0xae912852,0xb6f4b54c,0xb5dfb396,0xb8fdb842,0xb8d6b7d8,0xba41b9a8,0xba60b9a8,0xbb35bac6,0xbb71baf9,0xbbccbb8c,0xbbf5bbc6,0xbc00bbf3,0xbbe2bbff,
0xbc00bbed,0xbbdabb91,0xbbd3bbf7,0xbbf8bbfd,0xbb3dbb95,0xbb78bbcb,0xba45bacc,0xba64baff,0xb8f8b9a8,0xb8d1b9a8,0xb6d2b838,0xb5bcb7c2,0xb2adb51d,0xad97b334,0x251bae14,0x32192aac,
0xa94db115,0xb2c6b593,0x32322ce7,0x2c9cac83,0x36af34ed,0x359932d2,0x38f3382d,0x38cc37ac,0x3a4939a8,0x3a6739a8,0x3b453ad3,0x3b7f3b05,0x3bd93b9d,0x3bfb3bd1,0x3bfe3bfa,0x3bd23bfb,
0x3bfc3bdd,0x3bc83b6e,0x3bdf3bfd,0x3bfd3bf8,0x3b4c3ba4,0x3b853bd6,0x3a4d3ad9,0x3a6b3b0b,0x38ee39a8,0x38c739a8,0x368d3822,0x35763796,0x31b634bd,0x2b43326f,0xac062b75,0xb371adb0,
0x340e364e,0x36a43887,0xa94d2edc,0x2d333408,0xb552b20d,0xb432ade2,0xb8c1b780,0xb899b6cc,0xba6fb9a8,0xba8cb9a8,0xbb8bbb11,0xbbb8bb3e,0xbbfebbdb,0xbbf9bbf7,0xbbbdbbf4,0xbb47bbbe,
0xbbb2bb46,0xbb35ba7c,0xbbffbbf0,0xbbf6bbb4,0xbb92bbe0,0xbbbdbbf9,0xba73bb17,0xba90bb43,0xb8bcb9a8,0xb894b9a8,0xb52fb76a,0xb40eb6b5,0xa6adb1aa,0x2e2dad1a,0x34633004,0x36f43451,
0xb4b7b705,0xb742b8d8,0x217fb099,0xaf27b499,0x350b3147,0x33d32c51,0x38b73753,0x388e369e,0x3a7639a8,0x3a9339a8,0x3b983b1d,0x3bc23b49,0x3c003be4,0x3bf33bfb,0x3ba53beb,0x3b213baa,
0x3b983b1a,0x3b0d3a3f,0x3c003be5,0x3bef3b9e,0x3b9e3be8,0x3bc63bfd,0x3a7a3b22,0x3a973b4e,0x38b239a8,0x388939a8,0x34e7373d,0x33893687,0x9cb630e4,0xb0102b11,0xb50bb12e,0xb790b4e1,
0x355e37b7,0x37dd3927,0x251b31c3,0x308d3529,0xb4c3b080,0xb340a97f,0xb8adb726,0xb884b670,0xba7eb9a8,0xba9bb9a8,0xbba3bb28,0xbbcbbb53,0xbc00bbec,0xbbebbbfe,0xbb89bbdf,0xbaf7bb93,
0xbb7abae9,0xbae1b9fe,0xbbffbbd7,0xbbe6bb86,0xbba9bbef,0xbbcfbbff,0xba81bb2e,0xba9ebb58,0xb8a8b9a8,0xb87fb9a8,0xb49fb710,0xb2f7b659,0x2884b01d,0x3109a7da,0x35b13257,0x38153570,
0xb602b832,0xb83ab972,0xaa7ab2ea,0xb185b5b6,0x347b2f72,0x32ad24b6,0x38a336f9,0x387a3642,0x3a8539a8,0x3aa239a8,0x3bae3b33,0x3bd33b5d,0x3bfd3bf2,0x3be13c00,0x3b6a3bd0,0x3acb3b79,
0x3b593ab5,0x3ab339ba,0x3bfc3bc7,0x3bdc3b6b,0x3bb33bf5,0x3bd73c00,0x3a893b39,0x3aa53b62,0x389e39a8,0x387439a8,0x345736e3,0x3263362b,0xac382eaa,0xb2011e48,0xb654b37d,0xb85fb5fd,
0xb99ab997,0xb89fb873,0xb99eb99c,0xb8f5b8ca,0xb9a3b9a0,0xb947b91e,0xb9a7b9a5,0xb995b96e,0xb9abb9a9,0xb9e0b9bb,0xb9b0b9ae,0xba26ba03,0xb9b4b9b2,0xba68ba48,0xb9b9b9b7,0xbaa6ba88,
0xb9d3b9d9,0xba9fbac0,0xb9c6b9cc,0xba59ba7d,0xb9b9b9bf,0xba0eba34,0xb9abb9b2,0xb9bdb9e6,0xb99eb9a5,0xb967b993,0xb991b997,0xb90db93b,0xb983b98a,0xb8aeb8de,0xb975b97c,0xb84cb87e,
0x395e3953,0x385c3824,0x3975396a,0x38c83892,0x398c3981,0x392f38fc,0x39a33997,0x39913961,0x39b939ae,0x39ec39bf,0x39cf39c4,0x3a423a18,0x39e439d9,0x3a913a6a,0x39f939ef,0x3ad93ab6,
0x3a0a3a18,0x3acb3af0,0x39ec39fb,0x3a7b3aa4,0x39cf39de,0x3a223a4f,0x39b039bf,0x39c139f3,0x399139a0,0x395a398e,0x39713981,0x38eb3923,0x39503961,0x387638b1,0x392f3940,0x37f63839,
0xb921b90b,0xb816b7a4,0xb94bb936,0xb89ab859,0xb975b961,0xb917b8d9,0xb99eb98a,0xb98cb953,0xb9c6b9b2,0xb9f9b9c4,0xb9ecb9d9,0xba5dba2c,0xba12b9ff,0xbab7ba8b,0xba36ba24,0xbb07bae1,
0xba3eba53,0xbaf5bb1d,0xba12ba28,0xba9bbaca,0xb9e4b9fb,0xba36ba6a,0xb9b4b9cc,0xb9c6b9ff,0xb983b99c,0xb94bb98a,0xb950b96a,0xb8c8b90b,0xb91cb936,0xb83cb883,0xb8e6b901,0xb750b7e6,
0x38e138c0,0x379e36fc,0x39213901,0x386b381e,0x395e3940,0x38fe38b6,0x399a397c,0x39883944,0x39d339b7,0x3a0539c8,0x3a0a39ef,0x3a773a40,0x3a3e3a24,0x3adc3aab,0x3a703a57,0x3b333b09,
0x3a703a8b,0x3b1c3b47,0x3a363a53,0x3abb3aed,0x39f93a18,0x3a4a3a84,0x39b939d9,0x39ca3a0c,0x39753997,0x393d3985,0x392f3953,0x38a438f2,0x38e6390b,0x38003854,0x389a38c0,0x36a73756,
0xb70db651,0xb4aeb309,0xb83cb7c5,0xb6ebb5d1,0xb8e6b892,0xb880b7fb,0xb983b936,0xb971b8fc,0xba12b9cc,0xba42b9de,0xba91ba53,0xbaefba9d,0xbafebaca,0xbb74bb37,0xbb5abb2e,0xbbcebba6,
0xbb40bb6c,0xbbb2bbd8,0xbad9bb0f,0xbb43bb80,0xba5dba9d,0xbaa6bafa,0xb9cfba18,0xb9e0ba48,0xb92fb981,0xb8f5b96e,0xb880b8d9,0xb7d5b873,0xb788b824,0xb590b6b8,0xb5fab6c3,0xb251b460,
0x367935a2,0x34113197,0x380b374b,0x3684354f,0x38cd386e,0x386637af,0x397e3928,0x396c38ed,0x3a1e39d1,0x3a4e39e2,0x3aa93a66,0x3b043aaf,0x3b1f3ae7,0x3b8c3b4e,0x3b7d3b51,0x3be03bbd,
0x3b613b8d,0x3bc73be8,0x3af53b2e,0x3b5a3b97,0x3a703ab6,0x3ab73b0f,0x39d33a24,0x39e43a53,0x3921397c,0x38e6396a,0x385c38c0,0x37883859,0x370d37e6,0x350e3651,0x3549362e,0x30de3383,
0xb5e2b4f0,0xb2e4b023,0xb7b4b6cf,0xb61db4cc,0xb8b4b849,0xb84cb761,0xb97ab919,0xb967b8de,0xba2ab9d5,0xba59b9e6,0xbac1ba79,0xbb19bac0,0xbb3dbb03,0xbba2bb65,0xbb9cbb70,0xbbefbbd0,
0xbb7fbbaa,0xbbd8bbf4,0xbb10bb4c,0xbb6fbbac,0xba82bacd,0xbac8bb23,0xb9d7ba30,0xb9e8ba5f,0xb912b978,0xb8d7b965,0xb836b8a7,0xb73ab83e,0xb690b783,0xb48ab5e8,0xb496b596,0xaecfb244,
0x3549343b,0x31a42d58,0x37503651,0x35b33447,0x389a3824,0x38313713,0x3975390b,0x396338cf,0x3a3639d9,0x3a6539ea,0x3ad93a8b,0x3b2d3ad0,0x3b5a3b1d,0x3bb53b7a,0x3bb73b8d,0x3bf93be0,
0x3b9a3bc3,0x3be73bfc,0x3b2a3b67,0x3b833bbe,0x3a943ae4,0x3ad93b37,0x39db3a3c,0x39ec3a6a,0x39033973,0x38c83961,0x3811388d,0x36eb3824,0x3611371e,0x3405357e,0x33c034fc,0x2bc03103,
0xb061a8cf,0x25b230ac,0xb549b383,0xb32eae84,0xb816b6c3,0xb750b57e,0xb95eb8c0,0xb94bb883,0xba70b9ef,0xba9bb9ff,0xbb40bae1,0xbb83bb1d,0xbbc7bb8d,0xbbf5bbcc,0xbbffbbed,0xbbeabbff,
0xbbf2bc00,0xbbfebbe3,0xbb96bbcf,0xbbd2bbf9,0xbae9bb49,0xbb25bb8b,0xb9f1ba75,0xba01baa1,0xb8b9b95c,0xb87bb949,0xb69bb809,0xb555b734,0xb2fdb514,0xad71b2bf,0xa376af7e,0x31662966,
0x2e39a052,0xabf2b21f,0x34de3276,0x32512c5e,0x37f63673,0x3718352c,0x395a38b1,0x39473873,0x3a7b39f3,0x3aa63a03,0x3b523af0,0x3b923b2c,0x3bd63b9f,0x3bfb3bd8,0x3c003bf6,0x3bda3bfc,
0x3bfa3bff,0x3bf93bd1,0x3ba73bdd,0x3bdd3bfd,0x3af83b5b,0x3b333b99,0x39f53a80,0x3a053aab,0x38a93957,0x386b3944,0x364b37db,0x350236fc,0x31ee34a8,0x2a9331e2,0xa8062cf4,0xb2d8ad3f,
0xab5c2af8,0x2e843390,0xb472b166,0xb172a86b,0xb7bfb622,0xb6e0b4d8,0xb955b8a2,0xb942b863,0xba86b9f7,0xbab0ba08,0xbb64bb00,0xbba0bb39,0xbbe3bbaf,0xbbffbbe2,0xbbfdbbfd,0xbbc6bbf5,
0xbbffbbfa,0xbbf1bbba,0xbbb7bbe8,0xbbe7bc00,0xbb07bb6c,0xbb40bba6,0xb9f9ba8b,0xba0abab6,0xb89ab953,0xb85cb940,0xb5fab7a4,0xb4aeb6c3,0xb0deb43b,0xa484b103,0x2cf4a8cf,0x34232fc9,
0x2484ae6b,0xb086b47e,0x34053055,0x30931248,0x378835d1,0x36a73484,0x39503892,0x393d3854,0x3a9139fb,0x3abb3a0c,0x3b743b0f,0x3bad3b47,0x3bed3bbe,0x3c003beb,0x3bf63c00,0x3bae3beb,
0x3c003bf0,0x3be53ba0,0x3bc53bf2,0x3bef3c00,0x3b163b7c,0x3b4d3bb3,0x39fd3a96,0x3a0e3ac0,0x388b394e,0x384c393b,0x35a8376c,0x345a368a,0x2f97339c,0xa4203023,0xafe298b6,0xb4d8b128,
0x31c93531,0x355b37e0,0xaf652839,0x9d7f315a,0xb66db42f,0xb584b1b0,0xb939b844,0xb925b803,0xbac5ba10,0xbaecba20,0xbbb9bb53,0xbbdfbb82,0xbbffbbf2,0xbbe3bc00,0xbb91bbde,0xbaf7bb8a,
0xbbd6bb81,0xbb7cbadf,0xbbf5bbfd,0xbc00bbdd,0xbb5abbbe,0xbb88bbe3,0xba12baca,0xba22baf0,0xb83cb936,0xb7f6b923,0xb405b651,0xb15ab567,0x2a61ae84,0x31e22052,0x358a3269,0x381935a8,
0xb309b5e2,0xb5f4b841,0x2da3ac44,0xa5b2b269,0x363433b4,0x35493103,0x39343834,0x392137e6,0x3acf3a14,0x3af53a24,0x3bc43b60,0x3be73b8d,0x3bfb3bf8,0x3bd63bff,0x3b703bce,0x3ac63b6d,
0x3bc53b5f,0x3b5d3aad,0x3bfa3bf9,0x3bff3bcf,0x3b663bc9,0x3b923bea,0x3a163ad4,0x3a263afa,0x382c3931,0x37d5391e,0x335f3617,0x30ac352c,0xad582cc2,0xb2f0a89d,0xb63ab3a8,0xb869b63f,
0x34233690,0x368a3890,0xabc02e6b,0x2a613377,0xb5fab309,0xb50eb055,0xb92fb824,0xb91cb7c5,0xbad9ba18,0xbafeba28,0xbbcebb6c,0xbbedbb97,0xbbf6bbfc,0xbbc7bbfd,0xbb4cbbba,0xba93bb4d,
0xbbafbb38,0xbb3cba77,0xbbfebbf2,0xbbfcbbbf,0xbb72bbd3,0xbb9cbbf0,0xba1abadd,0xba2abb03,0xb81cb92d,0xb7b4b919,0xb2b3b5dc,0xaffbb4f0,0x2f7ea9fd,0x33fd2c12,0x36e53472,0x38b636d4,
0xb4c0b73a,0xb71eb8dc,0x2839b048,0xacf4b441,0x35bf325d,0x34d22f4c,0x392a3813,0x391737a4,0x3ae23a1c,0x3b073a2c,0x3bd73b77,0x3bf33ba1,0x3bee3bff,0x3bb63bfa,0x3b233ba4,0x3a5b3b2a,
0x3b973b0d,0x3b183a3e,0x3c003be9,0x3bf73bad,0x3b7d3bdb,0x3ba63bf5,0x3a1e3ae7,0x3a2e3b0c,0x380b3928,0x37933914,0x320735a2,0x2e9d34b4,0xb0d124e9,0xb484add5,0xb78eb50e,0xb901b767,
0xb97239ba,0x39dc3996,0xb8323ab5,0x3ad0385d,0x3927b9fe,0xba1fb94d,0x37b7bae9,0xbb02b807,0xb8d83a3f,0x3a5e3900,0xb7053b1a,0x3b30375e,0x3887ba7c,0xba99b8b0,0x364ebb46,0xbb5ab6aa,
0xb90039dc,0x3a3f3972,0xad7e3be6,0x3bf83115,0x3807ba99,0xbae9b887,0xabd9bc00,0xbbfca248,0xb5f13b30,0x3b6e3705,0x32a13bed,0x3bd4b04e,0x3365bba0,0xbbc9b4d5,0xb593bbaf,0xbb803475,
0xb88739fe,0x3a99394d,0x35f13bbc,0x3b6eb414,0x3593bb1a,0xbb80b75e,0xb8b0bb02,0xba7c37b7,0xaf0e3bc9,0x3bf43365,0x3a1f39dc,0x3927b972,0xb04ebc00,0xbbed2248,0xbb30b85d,0xb7053ab5,
0xb8073a1f,0x3ae93927,0x39fe3a3f,0x394db900,0x31dbbb80,0xbbddb593,0xbb6eb832,0xb5f13ad0,0x31153c00,0x3be62248,0x3bff32a1,0x28b6bbd4,0xb7b7bb91,0xbb023534,0xbba0304e,0x34d53bed,
0xb7053a3f,0x3b303900,0x3bbc375e,0x3414bb1a,0x2248bbc9,0xbc00b365,0xbbdda8b6,0x31db3bff,0x36aa3bd4,0x3b46b2a1,0x3a7cb64e,0xb8b0bb5a,0xba1fba5e,0xb92738d8,0xb7b739fe,0x3b02394d,
0xb5f13a5e,0x3b6e38d8,0x3bd42bd9,0xb2a1bbfc,0xb115bbf4,0xbbe6af0e,0xb9dc375e,0x39723b1a,0x39273b46,0x3a1fb6aa,0x3475bad0,0xbbafb832,0xbb91b887,0xb5343a99,0x34143c00,0x3bbc2248,
0xb4d53a7c,0x3ba038b0,0x3a3fb593,0xb900bb80,0xb534bc00,0xbb912248,0xb4143ab5,0x3bbc385d,0x3a993a5e,0x3887b8d8,0xb5f1bbfc,0xbb6e2bd9,0xbbffb475,0x28b63baf,0x3ad03a1f,0x3832b927,
0xb3653a99,0x3bc93887,0x36aab996,0xbb46b9ba,0xb7b7bbed,0xbb02304e,0x34d53bfc,0x3ba02bd9,0x3b913927,0x3534ba1f,0xbae9ba3f,0xb8073900,0xbb5a28b6,0x364e3bff,0x3bd43115,0xb2a1bbe6,
0xb1153ab5,0x3be6385d,0xa8b6bb6e,0xbbffb5f1,0xb900bbbc,0xba3f3414,0x3a1f3b30,0x3927b705,0x3bfc375e,0x2bd9bb1a,0xbbedb475,0x304e3baf,0xb9ba3593,0x39963b80,0x3887b832,0xba99bad0,
0xad7e3ad0,0x3bf83832,0xb7b7bbff,0xbb0228b6,0xb9febb6e,0xb94d35f1,0x3bed3887,0x304eba99,0x3bd43414,0xb2a1bbbc,0xb9963534,0x39ba3b91,0xb6aa3900,0x3b463a3f,0xb115bba0,0xbbe6b4d5,
0xa2483ae9,0x3c003807,0xba99bb30,0xb8873705,0xbad0bb02,0xb83237b7,0x3b462d7e,0xb6aabbf8,0x3b1a28b6,0xb75ebbff,0xaf0e3a7c,0x3bf438b0,0xabd93ab5,0x3bfc385d,0xba5ebb5a,0xb8d8364e,
0x2bd93b02,0x3bfc37b7,0xbbedb927,0xb04e3a1f,0xbb6eba7c,0xb5f138b0,0x385db6aa,0xbab5bb46,0x39dcb1db,0xb972bbdd,0x38323c00,0x3ad02248,0x34d53bbc,0x3ba03414,0xbbf4b705,0x2f0e3b30,
0x304e3b1a,0x3bed375e,0xbb91b475,0x35343baf,0xbbd4b9dc,0xb2a13972,0x2248ba7c,0xbc00b8b0,0x3832b64e,0xbad0bb5a,0x3b803a99,0x3593b887,0x39003bfc,0x3a3fabd9,0xb9273414,0x3a1f3bbc,
0x32a13b30,0x3bd43705,0xb996304e,0x39ba3bed,0xbbffb927,0xa8b63a1f,0xb832bbf4,0xbad0af0e,0x3475b8b0,0xbbafba7c,0x3ba03593,0xb4d5bb80,0x3ae93b6e,0x3807b5f1,0x2bd93a99,0x3bfc3887,
0x34753b46,0x3baf36aa,0xb4d53832,0x3ba03ad0,0xbbedb85d,0x304e3ab5,0xbb30bb5a,0xb705364e,0x2248b9fe,0xbc00b94d,0x3887b414,0xba99bbbc,0x3be63a1f,0x3115b927,0x39dc3bf4,0x3972af0e,
0x35933b5a,0x3b80364e,0x31153a99,0x3be63887,0xbba0b705,0x34d53b30,0xbbf4b8d8,0x2f0e3a5e,0xb414bb02,0xbbbcb7b7,0xabd9ba1f,0xbbfcb927,0x3bd43832,0xb2a1bad0,0x3c003972,0xa248b9dc,
0x36aa3b6e,0x3b4635f1,0x38b03bdd,0x3a7c31db,0xbb1ab534,0x375e3b91,0xba3fb04e,0x39003bed,0xb807bbaf,0xbae9b475,0xb94dbbf8,0xb9fead7e,0x3ab53365,0xb85dbbc9,0x39ba28b6,0xb996bbff,
0x37b73b80,0x3b023593,0x3b1a3bc9,0x375eb365,0xba5eb2a1,0x38d83bd4,0xb53435f1,0x3b913b6e,0xb9babbfc,0xb996abd9,0xbbddbae9,0xb1db3807,0x38b0ad7e,0xba7cbbf8,0x28b6b900,0xbbffba3f,
0x385d3b91,0x3ab53534,0x3c003a5e,0x2248b8d8,0xb972ad7e,0x39dc3bf8,0x33653a3f,0x3bc93900,0xbb02bbe6,0xb7b73115,0xbb1ab6aa,0x375e3b46,0x3414b64e,0xbbbcbb5a,0xb94dbbdd,0xb9feb1db,
0x38d83ba0,0x3a5e34d5,0x3b3037b7,0xb705bb02,0xb85d28b6,0x3ab53bff,0x39ba3be6,0x39963115,0xbbc9bb6e,0xb36535f1,0xb6aa31db,0x3b463bdd,0xaf0eb94d,0xbbf4b9fe,0xbbf8bae9,0xad7e3807,
0x394d3baf,0x39fe3475,0x38d82d7e,0xba5ebbf8,0xb64e3115,0x3b5a3be6,0x3bd43b80,0x32a1b593,0xbbffba99,0x28b63887,0x336539ba,0x3bc93996,0xb75ebae9,0xbb1ab807,0xba3fb534,0x39003b91,
0x39ba3bbc,0x39963414,0x31dbb534,0xbbddbb91,0xb3653475,0x3bc93baf,0x3b803927,0xb593ba1f,0xbba0b972,0x34d539dc,0x3a3f3be6,0x39003115,0xb9febbd4,0xb94db2a1,0xb04e35f1,0x3bed3b6e,
0x3a1f3bc9,0x39273365,0xb475b972,0xbbafb9dc,0xabd9364e,0x3bfc3b5a,0x38d831db,0xba5ebbdd,0xbab5b807,0x385d3ae9,0x3c003b30,0x2248b705,0xbb80bbf4,0xb5932f0e,0x38b03b1a,0x3a7c375e,
0x3a7c3bd4,0x38b032a1,0xb972bb5a,0xb9dcb64e,0x2f0e3807,0x3bf43ae9,0x2d7eb534,0xbbf8bb91,0xb94db4d5,0x39fe3ba0,0x3a5e37b7,0xb8d8bb02,0xbc00bb46,0x224836aa,0x3bdd3bc9,0x31dbb365,
0x3ad03bdd,0x383231db,0xbb80bc00,0xb5932248,0x347538d8,0x3baf3a5e,0xb75eb9fe,0xbb1ab94d,0xb705ad7e,0x3b303bf8,0x3414af0e,0xbbbcbbf4,0xbb6eb9dc,0x35f13972,0x3ab538b0,0xb85dba7c,
0x3b1a3be6,0x375e3115,0xbbf4bb46,0x2f0e36aa,0x37053996,0x3b3039ba,0xbae9bbd4,0xb807b2a1,0xb1db304e,0x3bdd3bed,0xb64eb94d,0xbb5ab9fe,0xb9dcb7b7,0x39723b02,0x3365ad7e,0xbbc9bbf8,
0x3b5a3bed,0x364e304e,0xbab5b94d,0x385d39fe,0x38b03a3f,0x3a7c3900,0xbbffbba0,0x28b634d5,0x2d7e3593,0x3bf83b80,0xbb02bbc9,0xb7b7b365,0xb705b1db,0x3b303bdd,0xb807b9ba,0xbae9b996,
0x3b913bf4,0x35342f0e,0xb807b4d5,0x3ae93ba0,0x39ba3ad0,0x39963832,0xba99b972,0x388739dc,0x3593385d,0x3b803ab5,0xbbe6bb6e,0x311535f1,0xad7e304e,0x3bf83bed,0xbbafbbfc,0xb475abd9,
0x3bbc3bf8,0x34142d7e,0xabd92f0e,0x3bfc3bf4,0x3a993b46,0x388736aa,0xb64eb365,0x3b5a3bc9,0x38b039ba,0x3a7c3996,0xb972b85d,0x39dc3ab5,0x34753705,0x3baf3b30,0xbb1aba5e,0x375e38d8,
0x3bdd3bfc,0x31db2bd9,0x364e3807,0x3b5a3ae9,0x3b463ba0,0x36aa34d5,0x31153475,0x3be63baf,0x3a3f3ad0,0x39003832,0xad7e28b6,0x3bf83bff,0x38d83996,0x3a5e39ba,0xb534b2a1,0x3b913bd4,
0x3bf43bff,0x2f0e28b6,0x3a1f3a7c,0x392738b0,0x3bbc3bdd,0x341431db,0x394d39ba,0x39fe3996,0x3b5a3b91,0x364e3534,0x385d38d8,0x3ab53a5e,0x3ad03b1a,0x3832375e,0x36aa37b7,0x3b463b02,
0x3bff3c00,0x28b62248,0x3bc93bd4,0x336532a1,0x3bf83bfc,0x2d7e2bd9,0x3baf3bbc,0x34753414,0x3bed3bf4,0x304e2f0e,0x3b913ba0,0x353434d5,0x3bdd3be6,0x31db3115,0x3b6e3b80,0x35f13593,
0xb5933b6e,0x3b8035f1,0xb1153bdd,0x3be631db,0x34d5bb91,0xbba0b534,0x2f0ebbed,0xbbf4b04e,0xb4143baf,0x3bbc3475,0xabd93bf8,0x3bfc2d7e,0x32a1bbc9,0xbbd4b365,0x2248bbff,0xbc00a8b6,
0x37b73b46,0x3b02b6aa,0x3b1a3832,0x375ebad0,0xb8d8bab5,0xba5e385d,0xbb91b64e,0xb5343b5a,0x39ba39fe,0x3996b94d,0x3bdd3414,0x31dbbbbc,0xba7cb927,0xb8b03a1f,0xbbffaf0e,0xa8b63bf4,
0x3bd43534,0x32a1bb91,0x39bab8d8,0xb996ba5e,0xbbffad7e,0x28b63bf8,0xb8323a3f,0x3ad03900,0x3bafb115,0xb475bbe6,0x34d5bb46,0xbba0b6aa,0xbae9364e,0x38073b5a,0xabd93bdd,0x3bfc31db,
0x3a5eb75e,0xb8d8bb1a,0xb705bbaf,0xbb303475,0xb85d39dc,0x3ab53972,0x39ba3a7c,0x3996b8b0,0x3365bb5a,0xbbc9b64e,0xbb46b887,0xb6aa3a99,0x2f0e3bfc,0x3bf42bd9,0x3bf83414,0x2d7ebbbc,
0x2bd9bbaf,0xbbfcb475,0xbbedad7e,0x304e3bf8,0x35f13be6,0x3b6eb115,0x3ab5b593,0xb85dbb80,0xb9dcba99,0xb9723887,0xb83239ba,0x3ad03996,0x3ba03807,0x34d5bae9,0x2f0ebb91,0xbbf4b534,
0xb9babae9,0xb9963807,0xb1db3b30,0x3bdd3705,0x3bc937b7,0x3365bb02,0xb593bbf8,0xbb802d7e,0xbba028b6,0x34d53bff,0x3a3f3a7c,0x3900b8b0,0x394db85d,0xb9febab5,0xbbedb64e,0xb04e3b5a,
0xbbf8b365,0x2d7e3bc9,0x3b0239dc,0x37b7b972,0x39feb64e,0xb94dbb5a,0xbbedb1db,0x304e3bdd,0xb2a13ae9,0x3bd43807,0x39bab705,0xb996bb30,0xb6aabbf4,0xbb462f0e,0xb1153b1a,0x3be6375e,
0xb8b0385d,0x3a7c3ab5,0x39dcb5f1,0xb972bb6e,0xaf0ebbbc,0xbbf4b414,0xad7e3b30,0x3bf83705,0x39fe3b1a,0x394db75e,0xb8d8bbaf,0xba5e3475,0xbc00b593,0x22483b80,0x3bdd3832,0x31dbbad0,
0x33653bdd,0x3bc931db,0xb6aabc00,0xbb462248,0xbb02ba5e,0xb7b738d8,0x3ba0394d,0x34d5b9fe,0x3b912d7e,0xb534bbf8,0xbae92f0e,0x38073bf4,0xb64e3972,0x3b5a39dc,0x32a1ba7c,0xbbd4b8b0,
0x3b1a3a7c,0x375eb8b0,0xbbf4b593,0x2f0e3b80,0xbb30a248,0x37053c00,0x3807b85d,0xbae9bab5,0x31dbba5e,0xbbddb8d8,0x364e3bfc,0x3b5a2bd9,0x39723baf,0x39dcb475,0xbbc9b927,0xb3653a1f,
0x3b6e304e,0xb5f1bbed,0xb2a139fe,0x3bd4394d,0xb1153a3f,0x3be63900,0xb9dcbba0,0xb97234d5,0xba1fbb80,0xb9273593,0x3baf3365,0xb475bbc9,0x3b9131db,0xb534bbdd,0xb41439ba,0x3bbc3996,
0x3534b900,0xbb91ba3f,0x3ae93b1a,0x3807b75e,0x39ba3bc9,0x3996b365,0xba9928b6,0x38873bff,0xbb80b2a1,0x35933bd4,0xb115bb5a,0xbbe6b64e,0x2d7eba5e,0xbbf8b8d8,0x3baf39fe,0x3475b94d,
0xb807bbf8,0xbae9ad7e,0x39feaf0e,0xb94dbbf4,0x3bdd36aa,0xb1dbbb46,0x35f13bc9,0x3b6e3365,0xb11539ba,0x3be63996,0xbbffb85d,0x28b63ab5,0xbb02bb30,0xb7b73705,0x34d5b8d8,0xbba0ba5e,
0xbbddb9fe,0xb1db394d,0xb64ebbbc,0xbb5ab414,0x36aab75e,0xbb46bb1a,0x3be637b7,0xb115bb02,0x3a3f3bc9,0x3900b365,0xad7e39dc,0x3bf83972,0xba5ea248,0x38d83c00,0xbb91bab5,0xb534385d,
0xba3fa8b6,0x39003bff,0xbbf8b8b0,0x2d7e3a7c,0xb807bbdd,0xbae9b1db,0x2bd9b9ba,0xbbfcb996,0x3b6e3534,0xb5f1bb91,0x3bd43a5e,0x32a1b8d8,0x33653b1a,0x3bc9375e,0xb59337b7,0x3b803b02,
0xa8b63996,0x3bff39ba,0xb365385d,0x3bc93ab5,0xbbf8b9fe,0xad7e394d,0xbbafbae9,0xb4753807,0x304eb900,0xbbedba3f,0x3534b75e,0xbb91bb1a,0x3bdd3a7c,0x31dbb8b0,0x3b6e3b46,0x35f1b6aa,
0x39dc3c00,0x3972a248,0x3ad03bd4,0x3832b2a1,0xb9272bd9,0x3a1f3bfc,0xb7b73414,0x3b023bbc,0xba5ebbf4,0xb8d82f0e,0xbb30bba0,0xb70534d5,0x3887b115,0xba99bbe6,0x364eb593,0xbb5abb80,
0x3bf43972,0xaf0eb9dc,0x3a1f3115,0xb927bbe6,0x34143a99,0x3bbc3887,0x39fe3c00,0x394d2248,0xbb5ab705,0x364e3b30,0xb85d304e,0x3ab53bed,0xb832bba0,0xbad0b4d5,0xbb46bbaf,0xb6aa3475,
0x3887abd9,0xba99bbfc,0xb5f1bae9,0xbb6eb807,0x3b803ba0,0x3593b4d5,0x3a7c3475,0xb8b0bbaf,0xaf0e3832,0x3bf43ad0,0x3a1f3bff,0x392728b6,0xbbedb996,0x304e39ba,0xb70532a1,0x3b303bd4,
0xb414ba1f,0xbbbcb927,0xbbfcba3f,0x2bd93900,0x3a993593,0xb887bb80,0xb64ebad0,0xbb5ab832,0x3a7c3c00,0x38b02248,0x39dc32a1,0xb972bbd4,0xb4753534,0x3baf3b91,0x3b1a3bed,0x375eb04e,
0xbb30bbf4,0xb7052f0e,0xb41434d5,0x3bbc3ba0,0x2248b832,0xbc00bad0,0xbbddb9dc,0x31db3972,0x3b46385d,0xb6aabab5,0xb8b0bb6e,0xba7cb5f1,0x3a1f3bed,0x3927304e,0x37b7abd9,0xbb02bbfc,
0xbb5ab8d8,0x364e3a5e,0x3ab53bfc,0x385d2bd9,0xba7cbbf4,0xb8b0af0e,0xa8b6375e,0x3bff3b1a,0x2d7eb6aa,0xbbf8bb46,0xbb02b832,0x37b73ad0,0x3b303887,0xb705ba99,0xbae9bc00,0xb807a248,
0xb4d53115,0x3ba03be6,0x3a3f36aa,0xb900bb46,0xbb91b996,0x353439ba,0x3bbc3bd4,0x3414b2a1,0xba99bbed,0xb887b04e,0x35f139fe,0x3b6e394d,0xa8b6b7b7,0xbbffbb02,0xb832ad7e,0x3ad03bf8,
0x38323a99,0x3ad03887,0xb593b996,0xbb80b9ba,0xb475304e,0x3baf3bed,0x375e2bd9,0xbb1abbfc,0xbb30b927,0x37053a1f,0x3bbc3a3f,0xb414b900,0xbb6ebbff,0xb5f128b6,0x3ab53be6,0x385d3115,
0x3be63bd4,0x3115b2a1,0xbbffbb5a,0x28b6364e,0x39003ae9,0x3a3f3807,0xba1fbb91,0xb927b534,0xabd934d5,0x3bfc3ba0,0xb04eb7b7,0xbbedbb02,0xb9bab6aa,0x39963b46,0x38873365,0xba99bbc9,
0x3a1f3832,0xb927bad0,0xb47528b6,0x3baf3bff,0x3bfc3b6e,0xabd9b5f1,0xba5eb887,0x38d83a99,0x3ab53bbc,0x385d3414,0xbc00bb91,0x22483534,0x35933900,0x3b803a3f,0xba7cbba0,0xb8b0b4d5,
0x2248b414,0xbc00bbbc,0x3a993b91,0x38873534,0x38323475,0xbad0bbaf,0x36aa3927,0x3b463a1f,0x3b1a39dc,0xb75eb972,0xaf0e3115,0x3bf43be6,0x3bfc3bd4,0x2bd9b2a1,0xb8d8b5f1,0x3a5e3b6e,
0xb9febb02,0xb94db7b7,0x3a5e3927,0xb8d8ba1f,0xb64eb8b0,0xbb5aba7c,0x3bd43b46,0xb2a1b6aa,0x28b6b1db,0xbbffbbdd,0x3bc93c00,0x33652248,0x375e3414,0xbb1abbbc,0x3a3f3b30,0x39003705,
0xbbedbba0,0x304e34d5,0xb534b7b7,0xbb91bb02,0xbbd4bbff,0xb2a1a8b6,0x2248b115,0xbc00bbe6,0xbad0bb6e,0xb832b5f1,0x359331db,0xbb80bbdd,0xb900b9fe,0xba3fb94d,0x39273807,0xba1fbae9,
0xb85db705,0x3ab53b30,0xbc00bbed,0x2248304e,0xb9dcb927,0x39723a1f,0xbbc9bbf4,0xb365af0e,0xbb02ba7c,0x37b738b0,0xbb1abb80,0xb75eb593,0xbbbcbb6e,0x341435f1,0xb9feba99,0xb94db887,
0x34753593,0x3baf3b80,0xb4d5b365,0x3ba03bc9,0x304e32a1,0x3bed3bd4,0xb705b5f1,0x3b303b6e,0xa2482bd9,0x3c003bfc,0xb887b807,0x3a993ae9,0xb115ad7e,0x3be63bf8,0xb972b900,0x39dc3a3f,
0x3b463b5a,0x36aa364e,0x3a7c3a99,0x38b03887,0x3b1a3b30,0x375e3705,0x3a3f3a5e,0x390038d8,0x3ae93b02,0x380737b7,0x39fe3a1f,0x394d3927,0x3ab53ad0,0x385d3832,0x39ba39dc,0x39963972,
0x28b63c00,0x3bffa248,0x33653bd4,0x3bc9b2a1,0xad7ebbfc,0xbbf82bd9,0xb475bbbc,0xbbaf3414,0x304e3bf4,0x3bedaf0e,0x35343ba0,0x3b91b4d5,0xb1dbbbe6,0xbbdd3115,0xb5f1bb80,0xbb6e3593,
0x3bf4a8b6,0xaf0ebbff,0x3a1fb8b0,0xb927ba7c,0xbbbc31db,0x34143bdd,0xb94d3996,0x39fe39ba,0x3b5ab534,0xb64ebb91,0x385dba5e,0xbab5b8d8,0xbad0375e,0x38323b1a,0xb6aa3b02,0x3b4637b7,
0xb1dbbbfc,0xbbdd2bd9,0xbb5ab807,0xb64e3ae9,0x36aa3ba0,0x3b46b4d5,0x3be63475,0x3115bbaf,0xb900bad0,0xba3f3832,0xbbf8a8b6,0x2d7e3bff,0x3a5e3996,0x38d8b9ba,0x3b91b2a1,0xb534bbd4,
0xbbbc2d7e,0x34143bf8,0x2bd93bf4,0x3bfc2f0e,0x3a99b6aa,0xb887bb46,0xb64ebbc9,0xbb5a3365,0xb8b03996,0x3a7c39ba,0x39723ab5,0x39dcb85d,0x3475bb30,0xbbafb705,0xbb1ab8d8,0xb75e3a5e,
0x35343bf4,0x3b91af0e,0x3ae9b4d5,0xb807bba0,0xb996bad0,0xb9ba3832,0xb8873972,0x3a9939dc,0x3b80385d,0x3593bab5,0x3115bb6e,0xbbe6b5f1,0xbbf8b04e,0x2d7e3bed,0x34753bfc,0x3bafabd9,
0x3b5ab04e,0xb64ebbed,0xbab5b9fe,0xb85d394d,0xb8b03900,0x3a7c3a3f,0x3bff34d5,0x28b6bba0,0x2d7ebb80,0xbbf8b593,0xbb023365,0x37b73bc9,0x37053bdd,0x3b30b1db,0x3807b996,0xbae9b9ba,
0xb75ebbe6,0xbb1a3115,0xaf0e3b46,0x3bf436aa,0x3b303996,0x3705b9ba,0xb807bbd4,0xbae932a1,0xbbddb04e,0x31db3bed,0x3b5a394d,0x364eb9fe,0x3972b7b7,0xb9dcbb02,0xbbc9ad7e,0x33653bf8,
0xbad031db,0x38323bdd,0x3b802248,0xb593bc00,0x3475ba5e,0xbbafb8d8,0xb75e394d,0x3b1a39fe,0x37053bf8,0x3b30ad7e,0xb414bbf4,0xbbbcaf0e,0xbb6eb972,0xb5f139dc,0x3ab53a7c,0x385db8b0,
0x38b03bd4,0x3a7cb2a1,0xb9dcbb5a,0xb972364e,0xbbf4b807,0xaf0e3ae9,0x3bf83534,0xad7ebb91,0x39feb4d5,0xb94dbba0,0xb8d837b7,0x3a5e3b02,0xa2483b46,0x3c0036aa,0xb1dbbbc9,0xbbddb365,
0x3a1fb365,0xb927bbc9,0xb47539dc,0x3baf3972,0x2bd93b5a,0x3bfc364e,0xb8d8bbdd,0xba5e31db,0xbab5bae9,0xb85d3807,0x3c003705,0xa248bb30,0x3b802f0e,0xb593bbf4,0xb8b0375e,0x3a7c3b1a,
0xb996bbbc,0xb9ba3414,0x3bdd3534,0xb1dbbb91,0x3bc93475,0xb365bbaf,0xb5933927,0x3b803a1f,0xb4d53972,0x3ba039dc,0xb900bbe6,0xba3f3115,0xb94dbbd4,0xb9fe32a1,0x3bed35f1,0xb04ebb6e,
0xb94d3475,0x39fe3baf,0xb8d8bbf8,0xba5e2d7e,0xb64ebbe6,0xbb5ab115,0x3bd43593,0xb2a1bb80,0x3bff3887,0x28b6ba99,0xb3653996,0x3bc939ba,0xb75e3807,0x3b1a3ae9,0xba3fbb91,0xb9003534,
0x3a5e3ba0,0x38d8b4d5,0xb70537b7,0x3b303b02,0xbab5a8b6,0x385d3bff,0xb996bbe6,0xb9ba3115,0xb365bb6e,0xbbc9b5f1,0x3b4631db,0xb6aabbdd,0x3bf4394d,0x2f0eb9fe,0x2d7e3ae9,0x3bf83807,
0x385db534,0xbab5bb91,0x3c0038d8,0xa248ba5e,0x39723bf8,0x39dcad7e,0xb3653900,0x3bc93a3f,0xbb02b115,0x37b73be6,0xbb1abb46,0xb75e36aa,0xb414bb5a,0xbbbcb64e,0x394db1db,0xb9febbdd,
0xbb02bb80,0xb7b73593,0xb75ebbc9,0xbb1ab365,0x38d8b2a1,0xba5ebbd4,0x3b9135f1,0xb534bb6e,0x39963bfc,0x39baabd9,0x31db3ae9,0x3bdd3807,0xba7cad7e,0x38b03bf8,0xbbffb900,0x28b63a3f,
0xb6aa35f1,0x3b463b6e,0xb8b031db,0x3a7c3bdd,0xbb1abb91,0xb75e3534,0xba3fbbed,0xb900304e,0x3807b475,0xbae9bbaf,0x394dad7e,0xb9febbf8,0x3ab53bc9,0x385db365,0x39ba3bff,0x3996a8b6,
0x3b803b5a,0x3593b64e,0x3be63a99,0x3115b887,0xb4d53705,0x3ba03b30,0xaf0e38d8,0x3bf43a5e,0xbbbcbb02,0xb41437b7,0xbbfcba1f,0xabd93927,0x32a1b832,0xbbd4bad0,0x2248b972,0xbc00b9dc,
0x3475b6aa,0xbbafbb46,0xb4d5bad0,0xbba0b832,0x3bed3ab5,0x304eb85d,0x3b30364e,0xb705bb5a,0x2248394d,0x3c0039fe,0x38873bbc,0x3a993414,0xbbe6b927,0x31153a1f,0xb9dcaf0e,0x39723bf4,
0xbbd4bb30,0xb2a13705,0xb9bab04e,0x39963bed,0xa8b6b927,0xbbffba1f,0xbad0bbf4,0xb8322f0e,0x3baf38b0,0xb475ba7c,0x34d5b593,0xbba0bb80,0x38073b6e,0x3ae935f1,0x3bfc3a99,0x2bd9b887,
0xb04e375e,0x3bed3b1a,0x3b913baf,0x3534b475,0xbbd4b972,0x32a139dc,0x224838b0,0x3c003a7c,0xb832bb5a,0xbad0b64e,0xbb80b887,0x35933a99,0x39002bd9,0xba3fbbfc,0xb927bbbc,0xba1fb414,
0x3bfc3b02,0x2bd9b7b7,0xb04eb927,0xbbedba1f,0x35f13a7c,0x3b6e38b0,0x3ab536aa,0xb85dbb46,0xb972b1db,0x39dc3bdd,0x3ad03c00,0x3832a248,0xbba0bbbc,0xb4d53414,0xaf0e3705,0x3bf43b30,
0xa248b807,0xbc00bae9,0xba99b705,0x38873b30,0x3ad037b7,0xb832bb02,0xbb46bbf8,0xb6aa2d7e,0x3b1a3bff,0x375ea8b6,0xaf0eb8b0,0xbbf4ba7c,0x2bd9385d,0x3bfc3ab5,0x3a5e364e,0xb8d8bb5a,
0xbbf8bad0,0x2d7e3832,0x3b023bff,0x37b728b6,0xb94dbb6e,0xb9feb5f1,0x304e3887,0x3bed3a99,0x32a1b414,0xbbd4bbbc,0xb9bab534,0x39963b91,0x3b463900,0xb6aaba3f,0xbbe6bba0,0xb11534d5,
0x3115385d,0x3be63ab5,0x28b6b5f1,0xbbffbb6e,0xb900b414,0x3a3f3bbc,0x3a1f3705,0xb927bb30,0xbbfcbb1a,0x2bd9375e,0x3bed3baf,0x304eb475,0xb9babb80,0xb996b593,0x38873ad0,0x3a993832,
0x3bc93a99,0xb365b887,0xbb46b996,0x36aa39ba,0x3b023bed,0x37b7304e,0xbba0bbfc,0xb4d52bd9,0x35343927,0x3b913a1f,0xb807ba3f,0xbae9b900,0xb64ea8b6,0x3b5a3bff,0x32a1b115,0xbbd4bbe6,
0xb4d5b8b0,0xbba0ba7c,0x3a3f3b80,0x39003593,0x35342248,0xbb91bc00,0x3414385d,0x3bbc3ab5,0x3a9938d8,0xb887ba5e,0xb5f1abd9,0x3b6e3bfc,0x3bff3baf,0x28b6b475,0xbad0b927,0x38323a1f,
0xbb6eba5e,0x35f138d8,0x32a1abd9,0xbbd4bbfc,0xbbe6bbf4,0xb1152f0e,0x3972375e,0xb9dcbb1a,0xba1fbb46,0xb927b6aa,0x3baf3ad0,0xb475b832,0xb534b887,0xbb91ba99,0x3bbc3c00,0x3414a248,
0x37053900,0x3b303a3f,0xbbbcbb1a,0x3414375e,0x22483365,0x3c003bc9,0xbbddbbff,0xb1db28b6,0xb6aab2a1,0x3b463bd4,0xba7cbb5a,0xb8b0b64e,0xba1fb8d8,0x39273a5e,0xb7b7b94d,0xbb02b9fe,
0x3ae93a1f,0xb807b927,0x394d3a3f,0x39fe3900,0x3bdd3b80,0xb1dbb593,0x35f13832,0x3b6e3ad0,0x3be63c00,0x3115a248,0x28b632a1,0x3bff3bd4,0x3b023b91,0x37b73534,0xb4d5b04e,0x3ba03bed,
0xb887b94d,0xba99b9fe,0x35f13414,0xbb6ebbbc,0xb593b75e,0xbb80bb1a,0x38b037b7,0xba7cbb02,0xaf0eb365,0xbbf4bbc9,0x3a1f3972,0xb927b9dc,0x304e2248,0xbbedbc00,0x3b303ab5,0xb705b85d,
0xba3fb9dc,0x39003972,0xbbf8bbe6,0x2d7e3115,0xbae9ba99,0x38073887,0xbbfcbc00,0xabd92248,0xbb6ebb30,0x35f13705,0xbbd4bbed,0xb2a1b04e,0xbbc9bba0,0x336534d5,0xbb80bbaf,0xb593b475,
0x39723996,0x39dc39ba,0x3832385d,0x3ad03ab5,0x3927394d,0x3a1f39fe,0x37b73807,0x3b023ae9,0x38d83900,0x3a5e3a3f,0x3705375e,0x3b303b1a,0x388738b0,0x3a993a7c,0x364e36aa,0x3b5a3b46,
0x36aa3b5a,0x3b46b64e,0x38b03a99,0x3a7cb887,0xb75ebb30,0xbb1a3705,0xb900ba5e,0xba3f38d8,0x38073b02,0x3ae9b7b7,0x394d3a1f,0x39feb927,0xb85dbad0,0xbab53832,0xb996b9dc,0xb9ba3972,
0x3475bb80,0xbbafb593,0xb4d5bbc9,0xbba03365,0xb04e3bd4,0x3bed32a1,0x37053b6e,0x3b30b5f1,0xa248bbfc,0xbc00abd9,0xb887bae9,0xba993807,0x31153bf8,0x3be6ad7e,0x39723a3f,0x39dcb900,
0xbab53705,0x385d3b30,0xa2483bed,0x3c00304e,0x3972b927,0xb9dcba1f,0xb365bbf4,0xbbc92f0e,0xb7b73a7c,0x3b0238b0,0x375e3b80,0x3b1ab593,0x3414bb6e,0xbbbcb5f1,0xb94dba99,0xb9fe3887,
0x3bed34d5,0x304ebba0,0x3534bb02,0xbb91b7b7,0xbbd428b6,0x32a13bff,0x22483be6,0x3c003115,0x3ad0b5f1,0xb832bb6e,0xb593bbdd,0xbb8031db,0xb900394d,0x3a3f39fe,0x39273ae9,0x3a1fb807,
0xb94dbb02,0xb9fe37b7,0xb8d83927,0x3a5e3a1f,0x3b5a38b0,0x364eba7c,0x32a1bb46,0xbbd4b6aa,0xbbffb1db,0x28b63bdd,0x33653c00,0x3bc9a248,0x3b1ab414,0xb75ebbbc,0xb900bb30,0xba3f3705,
0x22483bbc,0x3c003414,0x3a99b534,0xb887bb91,0xb832bbaf,0xbad03475,0xb6aa3a1f,0x3b463927,0x3b1a3972,0x375eb9dc,0xaf0ebbe6,0xbbf4b115,0xbbfcb2a1,0x2bd93bd4,0x38d83b6e,0x3a5eb5f1,
0x3927b832,0xba1fbad0,0xbbafa8b6,0x34753bff,0xabd93b6e,0x3bfc35f1,0x38d8b887,0xba5eba99,0xb85dbbbc,0xbab53414,0xa2483b91,0x3c003534,0x3b803900,0x3593ba3f,0xb8b0bba0,0xba7c34d5,
0xbbe6b2a1,0x31153bd4,0x3bff364e,0x28b6bb5a,0x3900b807,0xba3fbae9,0xba1f3534,0x39273b91,0x2bd93ba0,0x3bfc34d5,0x304ebb02,0xbbedb7b7,0xb9babb46,0xb99636aa,0x38873bc9,0x3a99b365,
0x3ad03a99,0x3832b887,0xbb80b996,0xb59339ba,0xbbafb04e,0x34753bed,0x3b1aabd9,0xb75ebbfc,0x3705b927,0xbb30ba1f,0xb4143a3f,0x3bbc3900,0x35f13bff,0x3b6e28b6,0xb85dbbe6,0xbab53115,
0xb4d5bbe6,0xbba0b115,0x3a3f3b46,0x3900b6aa,0x3b9139ba,0x3534b996,0xbbbcb2a1,0x34143bd4,0xba99304e,0x38873bed,0x35f1b94d,0xbb6eb9fe,0x28b6bb02,0xbbffb7b7,0x38323bf8,0x3ad0ad7e,
0xb64e38d8,0x3b5a3a5e,0xb85dbbfc,0xbab52bd9,0xb8b0bbf4,0xba7c2f0e,0x3bff375e,0xa8b6bb1a,0x3bf836aa,0xad7ebb46,0xb7b73832,0x3b023ad0,0xb7053887,0x3b303a99,0xb807bc00,0xbae92248,
0x3b302f0e,0xb705bbf4,0x34143ba0,0x3bbc34d5,0x22483ad0,0x3c003832,0xbbddb972,0xb1db39dc,0xbb46bab5,0xb6aa385d,0x38b0b5f1,0xba7cbb6e,0x3a1fb04e,0xb927bbed,0x37b73bfc,0x3b022bd9,
0xbbbcba1f,0xb4143927,0x2bd9ba3f,0xbbfcb900,0x3887b593,0xba99bb80,0x3b5a3ad0,0x364eb832,0x38b03c00,0x3a7ca248,0xb97232a1,0x39dc3bd4,0xbbafb534,0x34753b91,0xb75ebbed,0xbb1ab04e,
0x38873bfc,0x3a992bd9,0xb5f13807,0x3b6e3ae9,0xbb80b4d5,0x35933ba0,0xba7cbbaf,0xb8b03475,0xaf0ebad0,0xbbf4b832,0x3a1fa8b6,0xb927bbff,0x3bed39ba,0x304eb996,0x37053bd4,0x3b3032a1,
0x2f0eb972,0xbbf4b9dc,0x3927b115,0xba1fbbe6,0x3bbc3a99,0x3414b887,0x394d3c00,0x39fea248,0xb64e3705,0x3b5a3b30,0xbab5b04e,0x385d3bed,0xbad0bba0,0xb83234d5,0xb6aabbaf,0xbb46b475,
0xb9dca248,0x39723c00,0xbad0b2a1,0x38323bd4,0xb927bbfc,0xba1fabd9,0xb7b7bbbc,0xbb02b414,0x3a5e2f0e,0xb8d8bbf4,0x3b3034d5,0xb705bba0,0x38873be6,0x3a993115,0x364e3b80,0x3b5a3593,
0x3bff3996,0xa8b6b9ba,0x3bc9385d,0xb365bab5,0x2d7e39fe,0x3bf8394d,0x34753ae9,0x3baf3807,0xbbedb900,0x304e3a3f,0xbb91b75e,0x35343b1a,0xb1dbba7c,0xbbddb8b0,0xb5f1bb46,0xbb6eb6aa,
0xba3fbbff,0xb90028b6,0xbbf8ba7c,0xad7e38b0,0x3807b1db,0xbae9bbdd,0xabd9b996,0xbbfcb9ba,0x3b6e3b91,0x35f1b534,0x3bd438d8,0xb2a1ba5e,0xb365375e,0x3bc93b1a,0x35933b02,0x3b8037b7,
0x31db39fe,0x3bdd394d,0x3b5a3bbc,0x364eb414,0xbb46b75e,0x36aa3b1a,0xb11537b7,0x3be63b02,0xb900bbc9,0xba3fb365,0xbbf8b9dc,0x2d7e3972,0x38d8a248,0xba5ebc00,0xb534bab5,0xbb91b85d,
0x3807ad7e,0xbae9bbf8,0xb9febbf4,0xb94daf0e,0x3bdd3b46,0x31dbb6aa,0x35f1b365,0xbb6ebbc9,0x31153996,0x3be639ba,0x3bff3ab5,0x28b6b85d,0xbb02b705,0x37b73b30,0x34d53a5e,0x3ba038d8,
0xbb91b900,0x35343a3f,0x38073b1a,0x3ae9375e,0xb996bbc9,0xb9bab365,0xb887a8b6,0x3a993bff,0x3593b2a1,0xbb80bbd4,0xbbe6bb5a,0xb115364e,0x3bf83a5e,0xad7eb8d8,0xb475b9fe,0xbbafb94d,
0x3b6e3bed,0x35f1b04e,0xb2a1b94d,0xbbd4b9fe,0x31153900,0x3be63a3f,0x39dc34d5,0xb972bba0,0xba1fb593,0x39273b80,0x3baf3bc9,0x3475b365,0xbb91bbdd,0xb53431db,0x34143996,0x3bbc39ba,
0xb75eba7c,0xbb1ab8b0,0xaf0e3593,0x3bf43b80,0x3705a248,0xbb30bc00,0xbae9b85d,0x38073ab5,0x3bdd3a5e,0xb1dbb8d8,0xbb5abbfc,0xb64e2bd9,0x39dc3baf,0x39723475,0xb365b927,0xbbc9ba1f,
0xb36531db,0x3bc93bdd,0x36aa2248,0xbb46bc00,0xbb02b8d8,0x37b73a5e,0x3ba039fe,0xb4d5b94d,0xbb91bbf8,0xb5342d7e,0x3ae93bf4,0x38072f0e,0xb64eb9dc,0xbb5ab972,0x32a138b0,0x3bd43a7c,
0x3a7c385d,0xb8b0bab5,0xb972b5f1,0x39dc3b6e,0x3bf43bbc,0x2f0eb414,0xbbf8bb30,0x2d7e3705,0x394d3b1a,0x39fe375e,0xba5ebbaf,0xb8d8b475,0xa2483593,0x3c003b80,0xb1dbb832,0xbbddbad0,
0xbbf8bbc9,0xad7e3365,0x3b023972,0xb7b7b9dc,0xb9febb5a,0xb94db64e,0x3bed3bdd,0x304eb1db,0xb2a1b807,0xbbd4bae9,0x39ba3b30,0x39963705,0x36aa2f0e,0xbb46bbf4,0x3115375e,0x3be63b1a,
0x39963ae9,0x39ba3807,0xbbddbb30,0x31db3705,0x336537b7,0x3bc93b02,0xbb80bbf8,0xb593ad7e,0xb4d5a8b6,0x3ba03bff,0xb900ba7c,0xba3fb8b0,0xb9feb85d,0x394d3ab5,0xb04eb64e,0xbbedbb5a,
0xabd9b475,0xbbfcbbaf,0x3bed3bf8,0x304ead7e,0x35f13115,0xbb6ebbe6,0x3ab53b80,0x385d3593,0x39dc3887,0xb972ba99,0x38323996,0x3ad039ba,0x3ba03ae9,0xb4d5b807,0x2f0e3534,0x3bf43b91,
0xb8d8b75e,0x3a5e3b1a,0xbb30bbaf,0xb705b475,0xbab5b9dc,0x385d3972,0xb996ba7c,0xb9bab8b0,0xbbc9bb5a,0x3365364e,0xb6aab887,0xbb46ba99,0xbbf4bbfc,0xaf0e2bd9,0xad7eb414,0xbbf8bbbc,
0x3bd43b91,0xb2a1b534,0x39ba3a5e,0x399638d8,0x3bff3bf8,0x28b6ad7e,0x38323900,0x3ad03a3f,0x3baf3be6,0x34753115,0x34d536aa,0x3ba03b46,0x3ae93b5a,0x3807364e,0x2bd931db,0x3bfc3bdd,
0xbb02bb46,0xb7b7b6aa,0xb75eb832,0xbb1abad0,0xba5ebab5,0xb8d8b85d,0xb534b64e,0xbb91bb5a,0xb996b9fe,0xb9bab94d,0xb1dbb414,0xbbddbbbc,0xb8b0b927,0xba7cba1f,0xa8b6af0e,0xbbffbbf4,
0x359335f1,0x3b803b6e,0x311531db,0x3be63bdd,0x34d53534,0x3ba03b91,0x2f0e304e,0x3bf43bed,0x34143475,0x3bbc3baf,0x2bd92d7e,0x3bfc3bf8,0x32a13365,0x3bd43bc9,0x224828b6,0x3c003bff,
0x40000,0x60002,0xc0008,0xe000a,0x380034,0x3a0036,0x40003c,0x42003e,0x6c0068,0x6e006a,0x740070,0x760072,0xa0009c,0xa2009e,0xa800a4,0xaa00a6,
0xd400d0,0xd600d2,0xdc00d8,0xde00da,0x1080104,0x10a0106,0x110010c,0x112010e,0x13c0138,0x13e013a,0x1440140,0x1460142,0x170016c,0x172016e,0x1780174,0x17a0176,
0x1a401a0,0x1a601a2,0x1ac01a8,0x1ae01aa,0x1d801d4,0x1da01d6,0x1e001dc,0x1e201de,0x20c0208,0x20e020a,0x2140210,0x2160212,0x240023c,0x242023e,0x2480244,0x24a0246,
0x2740270,0x2760272,0x27c0278,0x27e027a,0x2a802a4,0x2aa02a6,0x2b002ac,0x2b202ae,0x2dc02d8,0x2de02da,0x2e402e0,0x2e602e2,0x310030c,0x312030e,0x3180314,0x31a0316,
0x3440340,0x3460342,0x34c0348,0x34e034a,0x3780374,0x37a0376,0x380037c,0x382037e,0x3ac03a8,0x3ae03aa,0x3b403b0,0x3b603b2,0x3e003dc,0x3e203de,0x3e803e4,0x3ea03e6,
0x4140410,0x4160412,0x41c0418,0x41e041a,0x4480444,0x44a0446,0x450044c,0x452044e,0x47c0478,0x47e047a,0x4840480,0x4860482,0x4b004ac,0x4b204ae,0x4b804b4,0x4ba04b6,
0x4e404e0,0x4e604e2,0x4ec04e8,0x4ee04ea,0x5180514,0x51a0516,0x520051c,0x522051e,0x54c0548,0x54e054a,0x5540550,0x5560552,0x580057c,0x582057e,0x5880584,0x58a0586,
0x5b405b0,0x5b605b2,0x5bc05b8,0x5be05ba,0x5e805e4,0x5ea05e6,0x5f005ec,0x5f205ee,0x61c0618,0x61e061a,0x6240620,0x6260622,0x650064c,0x652064e,0x6580654,0x65a0656,
0x140010,0x160012,0x120010,0x440012,0x480044,0x4a0046,0x460044,0x780046,0x7c0078,0x7e007a,0x7a0078,0xac007a,0xb000ac,0xb200ae,0xae00ac,0xe000ae,
0xe400e0,0xe600e2,0xe200e0,0x11400e2,0x1180114,0x11a0116,0x1160114,0x1480116,0x14c0148,0x14e014a,0x14a0148,0x17c014a,0x180017c,0x182017e,0x17e017c,0x1b0017e,
0x1b401b0,0x1b601b2,0x1b201b0,0x1e401b2,0x1e801e4,0x1ea01e6,0x1e601e4,0x21801e6,0x21c0218,0x21e021a,0x21a0218,0x24c021a,0x250024c,0x252024e,0x24e024c,0x280024e,
0x2840280,0x2860282,0x2820280,0x2b40282,0x2b802b4,0x2ba02b6,0x2b602b4,0x2e802b6,0x2ec02e8,0x2ee02ea,0x2ea02e8,0x31c02ea,0x320031c,0x322031e,0x31e031c,0x350031e,
0x3540350,0x3560352,0x3520350,0x3840352,0x3880384,0x38a0386,0x3860384,0x3b80386,0x3bc03b8,0x3be03ba,0x3ba03b8,0x3ec03ba,0x3f003ec,0x3f203ee,0x3ee03ec,0x42003ee,
0x4240420,0x4260422,0x4220420,0x4540422,0x4580454,0x45a0456,0x4560454,0x4880456,0x48c0488,0x48e048a,0x48a0488,0x4bc048a,0x4c004bc,0x4c204be,0x4be04bc,0x4f004be,
0x4f404f0,0x4f604f2,0x4f204f0,0x52404f2,0x5280524,0x52a0526,0x5260524,0x5580526,0x55c0558,0x55e055a,0x55a0558,0x58c055a,0x590058c,0x592058e,0x58e058c,0x5c0058e,
0x5c405c0,0x5c605c2,0x5c205c0,0x5f405c2,0x5f805f4,0x5fa05f6,0x5f605f4,0x62805f6,0x62c0628,0x62e062a,0x62a0628,0x65c062a,0x660065c,0x662065e,0x65e065c,0x18065e,
0x180018,0x4c001a,0x1a0018,0x4c001a,0x4c004c,0x80004e,0x4e004c,0x80004e,0x800080,0xb40082,0x820080,0xb40082,0xb400b4,0xe800b6,0xb600b4,0xe800b6,
0xe800e8,0x11c00ea,0xea00e8,0x11c00ea,0x11c011c,0x150011e,0x11e011c,0x150011e,0x1500150,0x1840152,0x1520150,0x1840152,0x1840184,0x1b80186,0x1860184,0x1b80186,
0x1b801b8,0x1ec01ba,0x1ba01b8,0x1ec01ba,0x1ec01ec,0x22001ee,0x1ee01ec,0x22001ee,0x2200220,0x2540222,0x2220220,0x2540222,0x2540254,0x2880256,0x2560254,0x2880256,
0x2880288,0x2bc028a,0x28a0288,0x2bc028a,0x2bc02bc,0x2f002be,0x2be02bc,0x2f002be,0x2f002f0,0x32402f2,0x2f202f0,0x32402f2,0x3240324,0x3580326,0x3260324,0x3580326,
0x3580358,0x38c035a,0x35a0358,0x38c035a,0x38c038c,0x3c0038e,0x38e038c,0x3c0038e,0x3c003c0,0x3f403c2,0x3c203c0,0x3f403c2,0x3f403f4,0x42803f6,0x3f603f4,0x42803f6,
0x4280428,0x45c042a,0x42a0428,0x45c042a,0x45c045c,0x490045e,0x45e045c,0x490045e,0x4900490,0x4c40492,0x4920490,0x4c40492,0x4c404c4,0x4f804c6,0x4c604c4,0x4f804c6,
0x4f804f8,0x52c04fa,0x4fa04f8,0x52c04fa,0x52c052c,0x560052e,0x52e052c,0x560052e,0x5600560,0x5940562,0x5620560,0x5940562,0x5940594,0x5c80596,0x5960594,0x5c80596,
0x5c805c8,0x5fc05ca,0x5ca05c8,0x5fc05ca,0x5fc05fc,0x63005fe,0x5fe05fc,0x63005fe,0x6300630,0x6640632,0x6320630,0x6640632,0x6640664,0x1c0666,0x6660664,0x1c0666,
0x1c001c,0x50001e,0x1e001c,0x50001e,0x500050,0x840052,0x520050,0x840052,0x840084,0xb80086,0x860084,0xb80086,0xb800b8,0xec00ba,0xba00b8,0xec00ba,
0xec00ec,0x12000ee,0xee00ec,0x12000ee,0x1200120,0x1540122,0x1220120,0x1540122,0x1540154,0x1880156,0x1560154,0x1880156,0x1880188,0x1bc018a,0x18a0188,0x1bc018a,
0x1bc01bc,0x1f001be,0x1be01bc,0x1f001be,0x1f001f0,0x22401f2,0x1f201f0,0x22401f2,0x2240224,0x2580226,0x2260224,0x2580226,0x2580258,0x28c025a,0x25a0258,0x28c025a,
0x28c028c,0x2c0028e,0x28e028c,0x2c0028e,0x2c002c0,0x2f402c2,0x2c202c0,0x2f402c2,0x2f402f4,0x32802f6,0x2f602f4,0x32802f6,0x3280328,0x35c032a,0x32a0328,0x35c032a,
0x35c035c,0x390035e,0x35e035c,0x390035e,0x3900390,0x3c40392,0x3920390,0x3c40392,0x3c403c4,0x3f803c6,0x3c603c4,0x3f803c6,0x3f803f8,0x42c03fa,0x3fa03f8,0x42c03fa,
0x42c042c,0x460042e,0x42e042c,0x460042e,0x4600460,0x4940462,0x4620460,0x4940462,0x4940494,0x4c80496,0x4960494,0x4c80496,0x4c804c8,0x4fc04ca,0x4ca04c8,0x4fc04ca,
0x4fc04fc,0x53004fe,0x4fe04fc,0x53004fe,0x5300530,0x5640532,0x5320530,0x5640532,0x5640564,0x5980566,0x5660564,0x5980566,0x5980598,0x5cc059a,0x59a0598,0x5cc059a,
0x5cc05cc,0x60005ce,0x5ce05cc,0x60005ce,0x6000600,0x6340602,0x6020600,0x6340602,0x6340634,0x6680636,0x6360634,0x6680636,0x6680668,0x20066a,0x66a0668,0x20066a,
0x5d605d6,0x60a05d6,0x5d605d6,0x60a060a,0x60a060a,0x63e063e,0x60a060a,0x63e063e,0x63e063e,0x672063e,0x63e063e,0x6720672,0x6720672,0x280028,0x6720672,0x280028,
0x5060506,0x53a0506,0x5060506,0x53a053a,0x53a053a,0x56e056e,0x53a053a,0x56e056e,0x56e056e,0x5a2056e,0x56e056e,0x5a205a2,0x5a205a2,0x5d605d6,0x5a205a2,0x5d605d6,
0x4360436,0x46a0436,0x4360436,0x46a046a,0x46a046a,0x49e049e,0x46a046a,0x49e049e,0x49e049e,0x4d2049e,0x49e049e,0x4d204d2,0x4d204d2,0x5060506,0x4d204d2,0x5060506,
0x3660366,0x39a0366,0x3660366,0x39a039a,0x39a039a,0x3ce03ce,0x39a039a,0x3ce03ce,0x3ce03ce,0x40203ce,0x3ce03ce,0x4020402,0x4020402,0x4360436,0x4020402,0x4360436,
0x2960296,0x2ca0296,0x2960296,0x2ca02ca,0x2ca02ca,0x2fe02fe,0x2ca02ca,0x2fe02fe,0x2fe02fe,0x33202fe,0x2fe02fe,0x3320332,0x3320332,0x3660366,0x3320332,0x3660366,
0x1c601c6,0x1fa01c6,0x1c601c6,0x1fa01fa,0x1fa01fa,0x22e022e,0x1fa01fa,0x22e022e,0x22e022e,0x262022e,0x22e022e,0x2620262,0x2620262,0x2960296,0x2620262,0x2960296,
0xf600f6,0x12a00f6,0xf600f6,0x12a012a,0x12a012a,0x15e015e,0x12a012a,0x15e015e,0x15e015e,0x192015e,0x15e015e,0x1920192,0x1920192,0x1c601c6,0x1920192,0x1c601c6,
0x260026,0x5a0026,0x260026,0x5a005a,0x5a005a,0x8e008e,0x5a005a,0x8e008e,0x8e008e,0xc2008e,0x8e008e,0xc200c2,0xc200c2,0xf600f6,0xc200c2,0xf600f6,
0x5d405d4,0x60805d4,0x5d405d4,0x6080608,0x6080608,0x63c063c,0x6080608,0x63c063c,0x63c063c,0x670063c,0x63c063c,0x6700670,0x6700670,0x260026,0x6700670,0x260026,
0x5040504,0x5380504,0x5040504,0x5380538,0x5380538,0x56c056c,0x5380538,0x56c056c,0x56c056c,0x5a0056c,0x56c056c,0x5a005a0,0x5a005a0,0x5d405d4,0x5a005a0,0x5d405d4,
0x4340434,0x4680434,0x4340434,0x4680468,0x4680468,0x49c049c,0x4680468,0x49c049c,0x49c049c,0x4d0049c,0x49c049c,0x4d004d0,0x4d004d0,0x5040504,0x4d004d0,0x5040504,
0x3640364,0x3980364,0x3640364,0x3980398,0x3980398,0x3cc03cc,0x3980398,0x3cc03cc,0x3cc03cc,0x40003cc,0x3cc03cc,0x4000400,0x4000400,0x4340434,0x4000400,0x4340434,
0x2940294,0x2c80294,0x2940294,0x2c802c8,0x2c802c8,0x2fc02fc,0x2c802c8,0x2fc02fc,0x2fc02fc,0x33002fc,0x2fc02fc,0x3300330,0x3300330,0x3640364,0x3300330,0x3640364,
0x1c401c4,0x1f801c4,0x1c401c4,0x1f801f8,0x1f801f8,0x22c022c,0x1f801f8,0x22c022c,0x22c022c,0x260022c,0x22c022c,0x2600260,0x2600260,0x2940294,0x2600260,0x2940294,
0xf400f4,0x12800f4,0xf400f4,0x1280128,0x1280128,0x15c015c,0x1280128,0x15c015c,0x15c015c,0x190015c,0x15c015c,0x1900190,0x1900190,0x1c401c4,0x1900190,0x1c401c4,
0x240024,0x580024,0x240024,0x580058,0x580058,0x8c008c,0x580058,0x8c008c,0x8c008c,0xc0008c,0x8c008c,0xc000c0,0xc000c0,0xf400f4,0xc000c0,0xf400f4,
0x5d205d2,0x60605d2,0x5d205d2,0x6060606,0x6060606,0x63a063a,0x6060606,0x63a063a,0x63a063a,0x66e063a,0x63a063a,0x66e066e,0x66e066e,0x240024,0x66e066e,0x240024,
0x5020502,0x5360502,0x5020502,0x5360536,0x5360536,0x56a056a,0x5360536,0x56a056a,0x56a056a,0x59e056a,0x56a056a,0x59e059e,0x59e059e,0x5d205d2,0x59e059e,0x5d205d2,
0x4320432,0x4660432,0x4320432,0x4660466,0x4660466,0x49a049a,0x4660466,0x49a049a,0x49a049a,0x4ce049a,0x49a049a,0x4ce04ce,0x4ce04ce,0x5020502,0x4ce04ce,0x5020502,
0x3620362,0x3960362,0x3620362,0x3960396,0x3960396,0x3ca03ca,0x3960396,0x3ca03ca,0x3ca03ca,0x3fe03ca,0x3ca03ca,0x3fe03fe,0x3fe03fe,0x4320432,0x3fe03fe,0x4320432,
0x2920292,0x2c60292,0x2920292,0x2c602c6,0x2c602c6,0x2fa02fa,0x2c602c6,0x2fa02fa,0x2fa02fa,0x32e02fa,0x2fa02fa,0x32e032e,0x32e032e,0x3620362,0x32e032e,0x3620362,
0x1c201c2,0x1f601c2,0x1c201c2,0x1f601f6,0x1f601f6,0x22a022a,0x1f601f6,0x22a022a,0x22a022a,0x25e022a,0x22a022a,0x25e025e,0x25e025e,0x2920292,0x25e025e,0x2920292,
0xf200f2,0x12600f2,0xf200f2,0x1260126,0x1260126,0x15a015a,0x1260126,0x15a015a,0x15a015a,0x18e015a,0x15a015a,0x18e018e,0x18e018e,0x1c201c2,0x18e018e,0x1c201c2,
0x220022,0x560022,0x220022,0x560056,0x560056,0x8a008a,0x560056,0x8a008a,0x8a008a,0xbe008a,0x8a008a,0xbe00be,0xbe00be,0xf200f2,0xbe00be,0xf200f2,
0x5d005d0,0x60405d0,0x5d005d0,0x6040604,0x6040604,0x6380638,0x6040604,0x6380638,0x6380638,0x66c0638,0x6380638,0x66c066c,0x66c066c,0x220022,0x66c066c,0x220022,
0x5000500,0x5340500,0x5000500,0x5340534,0x5340534,0x5680568,0x5340534,0x5680568,0x5680568,0x59c0568,0x5680568,0x59c059c,0x59c059c,0x5d005d0,0x59c059c,0x5d005d0,
0x4300430,0x4640430,0x4300430,0x4640464,0x4640464,0x4980498,0x4640464,0x4980498,0x4980498,0x4cc0498,0x4980498,0x4cc04cc,0x4cc04cc,0x5000500,0x4cc04cc,0x5000500,
0x3600360,0x3940360,0x3600360,0x3940394,0x3940394,0x3c803c8,0x3940394,0x3c803c8,0x3c803c8,0x3fc03c8,0x3c803c8,0x3fc03fc,0x3fc03fc,0x4300430,0x3fc03fc,0x4300430,
0x2900290,0x2c40290,0x2900290,0x2c402c4,0x2c402c4,0x2f802f8,0x2c402c4,0x2f802f8,0x2f802f8,0x32c02f8,0x2f802f8,0x32c032c,0x32c032c,0x3600360,0x32c032c,0x3600360,
0x1c001c0,0x1f401c0,0x1c001c0,0x1f401f4,0x1f401f4,0x2280228,0x1f401f4,0x2280228,0x2280228,0x25c0228,0x2280228,0x25c025c,0x25c025c,0x2900290,0x25c025c,0x2900290,
0xf000f0,0x12400f0,0xf000f0,0x1240124,0x1240124,0x1580158,0x1240124,0x1580158,0x1580158,0x18c0158,0x1580158,0x18c018c,0x18c018c,0x1c001c0,0x18c018c,0x1c001c0,
0x200020,0x540020,0x200020,0x540054,0x540054,0x880088,0x540054,0x880088,0x880088,0xbc0088,0x880088,0xbc00bc,0xbc00bc,0xf000f0,0xbc00bc,0xf000f0,
0x30003000,0x30003000,0x30003000,0x30003000,0x30003000,0x30003000,0x30003000,0x30003000,0x0,0x0,0x0,0x0,0x0,0x0,0x0,0x0,
0x30003000,0x30003000,0x30003000,0x30003000,0x30003000,0x30003000,0x30003000,0x30003000,0x0,0x0,0x0,0x0,0x0,0x0,0x0,0x0,
0x2a1f2da8,0xaf64ada8,0xaa1fada8,0x2f642da8,0x2f643000,0xaa1f0000,0xaf64b000,0x2a1f8000,0x2f642da8,0x2a1f2da8,0xaf64ada8,0xaa1fada8,0x2a1f0000,0x2f643000,0xaa1f0000,0xaf64b000,
0x263e2c72,0xafd9aea7,0xa63eac72,0x2fd92ea7,0x2ea72fd9,0xac72a63e,0xaea7afd9,0x2c72263e,0x2fd92ea7,0x263e2c72,0xafd9aea7,0xa63eac72,0x2c72263e,0x2ea72fd9,0xac72a63e,0xaea7afd9,
0x2da80000,0xada80000,0x2da88000,0xada80000,0x2da83000,0xada8b000,0x2da83000,0xada8b000,0x2da83000,0xada8b000,0x2da83000,0xada8b000,0xada80000,0x2da88000,0xada80000,0x2da88000,
0x2f642a1f,0xaf64aa1f,0x2f642a1f,0xaf64aa1f,0x2a1f2f64,0xaa1faf64,0x2a1f2f64,0xaa1faf64,0x2a1f2f64,0xaa1faf64,0x2a1f2f64,0xaa1faf64,0xaf64aa1f,0x2f642a1f,0xaf64aa1f,0x2f642a1f,
0xaa1f2da8,0x2f642da8,0x2a1fada8,0xaf64ada8,0x2f640000,0xaa1fb000,0xaf640000,0x2a1f3000,0xaf64ada8,0xaa1f2da8,0x2f642da8,0x2a1fada8,0x2a1f3000,0x2f648000,0xaa1fb000,0xaf640000,
0xaea7263e,0x2c722fd9,0x2ea7a63e,0xac72afd9,0x2fd92c72,0x263eaea7,0xafd9ac72,0xa63e2ea7,0xac72afd9,0xaea7263e,0x2c722fd9,0x2ea7a63e,0xa63e2ea7,0x2fd92c72,0x263eaea7,0xafd9ac72,
0xada82da8,0xada82da8,0xada82da8,0xada82da8,0x2da8ada8,0x2da8ada8,0x2da8ada8,0x2da8ada8,0x2da82da8,0x2da82da8,0x2da82da8,0x2da82da8,0xada8ada8,0xada8ada8,0xada8ada8,0xada8ada8,
0x3000,0x3000,0x3000,0x80003000,0x8000b000,0x8000b000,0x8000b000,0x8000b000,0x30000000,0x30008000,0x30008000,0x30008000,0xb0000000,0xb0000000,0xb0000000,0xb0000000,
0x2ea7263e,0xac722fd9,0xaea7a63e,0x2c72afd9,0xafd92c72,0xa63eaea7,0x2fd9ac72,0x263e2ea7,0x2c72afd9,0x2ea7263e,0xac722fd9,0xaea7a63e,0x263e2ea7,0xafd92c72,0xa63eaea7,0x2fd9ac72,
0x2f64ada8,0x2a1f2da8,0xaf642da8,0xaa1fada8,0xaa1f3000,0xaf640000,0x2a1fb000,0x2f648000,0xaa1fada8,0x2f64ada8,0x2a1f2da8,0xaf642da8,0x2f640000,0xaa1f3000,0xaf640000,0x2a1fb000,
0xaa1f2f64,0x2a1faf64,0xaa1f2f64,0x2a1faf64,0x2f64aa1f,0xaf642a1f,0x2f64aa1f,0xaf642a1f,0xaf642a1f,0x2f64aa1f,0xaf642a1f,0x2f64aa1f,0xaa1f2f64,0x2a1faf64,0xaa1f2f64,0x2a1faf64,
0x2da80000,0xada80000,0x2da88000,0xada80000,0x2da8b000,0xada83000,0x2da8b000,0xada83000,0xada83000,0x2da8b000,0xada83000,0x2da8b000,0x2da88000,0xada80000,0x2da88000,0xada88000,
0xa63e2c72,0x2fd9aea7,0x263eac72,0xafd92ea7,0xaea72fd9,0x2c72a63e,0x2ea7afd9,0xac72263e,0xafd92ea7,0xa63e2c72,0x2fd9aea7,0x263eac72,0xac72263e,0xaea72fd9,0x2c72a63e,0x2ea7afd9,
0x2f64ada8,0x2a1fada8,0xaf642da8,0xaa1f2da8,0x2a1f0000,0x2f64b000,0xaa1f0000,0xaf643000,0xaa1f2da8,0x2f64ada8,0x2a1fada8,0xaf642da8,0xaf643000,0x2a1f8000,0x2f64b000,0xaa1f8000,
0xb0003000,0xb0003000,0xb0003000,0xb0003000,0xb0003000,0xb0003000,0xb0003000,0xb0003000,0x0,0x8000,0x8000,0x80008000,0x8000,0x8000,0x8000,0x8000,
0x80000000,0x80000000,0x80008000,0x80008000,0x80000000,0x80008000,0x80008000,0x80008000,0xb0003000,0xb0003000,0xb0003000,0xb0003000,0xb0003000,0xb0003000,0xb0003000,0xb0003000,
0xaa1f2da8,0x2f64ada8,0x2a1fada8,0xaf642da8,0xaf643000,0x2a1f0000,0x2f64b000,0xaa1f8000,0xaf642da8,0xaa1f2da8,0x2f64ada8,0x2a1fada8,0xaa1f0000,0xaf643000,0x2a1f0000,0x2f64b000,
0x2fd9aea7,0x263eac72,0xafd92ea7,0xa63e2c72,0x2c72a63e,0x2ea7afd9,0xac72263e,0xaea72fd9,0xa63e2c72,0x2fd9aea7,0x263eac72,0xafd92ea7,0xaea72fd9,0x2c72a63e,0x2ea7afd9,0xac72263e,
0xada80000,0x2da80000,0xada88000,0x2da80000,0xada83000,0x2da8b000,0xada83000,0x2da8b000,0xada83000,0x2da8b000,0xada83000,0x2da8b000,0x2da80000,0xada88000,0x2da88000,0xada88000,
0xaa1f2f64,0x2a1faf64,0xaa1f2f64,0x2a1faf64,0x2f64aa1f,0xaf642a1f,0x2f64aa1f,0xaf642a1f,0x2f64aa1f,0xaf642a1f,0x2f64aa1f,0xaf642a1f,0x2a1faf64,0xaa1f2f64,0x2a1faf64,0xaa1f2f64,
0x2a1f2da8,0xaf642da8,0xaa1fada8,0x2f64ada8,0xaf640000,0x2a1fb000,0x2f640000,0xaa1f3000,0x2f64ada8,0x2a1f2da8,0xaf642da8,0xaa1fada8,0xaa1f3000,0xaf648000,0x2a1fb000,0x2f640000,
0x2c72afd9,0x2ea7263e,0xac722fd9,0xaea7a63e,0x263e2ea7,0xafd92c72,0xa63eaea7,0x2fd9ac72,0xaea7a63e,0x2c72afd9,0x2ea7263e,0xac722fd9,0x2fd9ac72,0x263e2ea7,0xafd92c72,0xa63eaea7,
0x2da8ada8,0x2da8ada8,0x2da8ada8,0x2da8ada8,0xada82da8,0xada82da8,0xada82da8,0xada82da8,0x2da82da8,0x2da82da8,0x2da82da8,0x2da82da8,0xada8ada8,0xada8ada8,0xada8ada8,0xada8ada8,
0x80003000,0x80003000,0x80003000,0x3000,0xb000,0x8000b000,0xb000,0xb000,0xb0000000,0xb0008000,0xb0008000,0xb0008000,0x30000000,0x30000000,0x30000000,0x30008000,
0x2c722fd9,0x2ea7a63e,0xac72afd9,0xaea7263e,0x263eaea7,0xafd9ac72,0xa63e2ea7,0x2fd92c72,0xaea7263e,0x2c722fd9,0x2ea7a63e,0xac72afd9,0x2fd92c72,0x263eaea7,0xafd9ac72,0xa63e2ea7,
0xaf64ada8,0xaa1f2da8,0x2f642da8,0x2a1fada8,0x2a1f3000,0x2f648000,0xaa1fb000,0xaf648000,0x2a1fada8,0xaf64ada8,0xaa1f2da8,0x2f642da8,0xaf640000,0x2a1f3000,0x2f648000,0xaa1fb000,
0x2f642a1f,0xaf64aa1f,0x2f642a1f,0xaf64aa1f,0x2a1f2f64,0xaa1faf64,0x2a1f2f64,0xaa1faf64,0xaa1faf64,0x2a1f2f64,0xaa1faf64,0x2a1f2f64,0x2f642a1f,0xaf64aa1f,0x2f642a1f,0xaf64aa1f,
0xada80000,0x2da80000,0xada88000,0x2da88000,0xada8b000,0x2da83000,0xada8b000,0x2da83000,0x2da83000,0xada8b000,0x2da83000,0xada8b000,0xada88000,0x2da88000,0xada88000,0x2da80000,
0x2fd92ea7,0x263e2c72,0xafd9aea7,0xa63eac72,0x2c72263e,0x2ea72fd9,0xac72a63e,0xaea7afd9,0xa63eac72,0x2fd92ea7,0x263e2c72,0xafd9aea7,0xaea7afd9,0x2c72263e,0x2ea72fd9,0xac72a63e,
0xaf64ada8,0xaa1fada8,0x2f642da8,0x2a1f2da8,0xaa1f0000,0xaf64b000,0x2a1f0000,0x2f643000,0x2a1f2da8,0xaf64ada8,0xaa1fada8,0x2f642da8,0x2f643000,0xaa1f8000,0xaf64b000,0x2a1f0000,
0x80008000,0x80008000,0x80008000,0x80008000,0x80008000,0x80008000,0x80008000,0x80008000,0x30003000,0x30003000,0x30003000,0x30003000,0x30003000,0x30003000,0x30003000,0x30003000,
0x80008000,0x80008000,0x80008000,0x80008000,0x80008000,0x80008000,0x80008000,0x80008000,0x30003000,0x30003000,0x30003000,0x30003000,0x30003000,0x30003000,0x30003000,0x30003000,
0xaf64ada8,0xaa1fada8,0x2f642da8,0x2a1f2da8,0xaa1f8000,0xaf64b000,0x2a1f8000,0x2f643000,0x2a1f2da8,0xaf64ada8,0xaa1fada8,0x2f642da8,0x2f643000,0xaa1f0000,0xaf64b000,0x2a1f8000,
0xafd9aea7,0xa63eac72,0x2fd92ea7,0x263e2c72,0xac72a63e,0xaea7afd9,0x2c72263e,0x2ea72fd9,0x263e2c72,0xafd9aea7,0xa63eac72,0x2fd92ea7,0x2ea72fd9,0xac72a63e,0xaea7afd9,0x2c72263e,
0x2da83000,0xada8b000,0x2da83000,0xada8b000,0xada80000,0x2da88000,0xada80000,0x2da88000,0xada88000,0x2da88000,0xada80000,0x2da88000,0xada8b000,0x2da83000,0xada8b000,0x2da83000,
0x2a1f2f64,0xaa1faf64,0x2a1f2f64,0xaa1faf64,0xaf64aa1f,0x2f642a1f,0xaf64aa1f,0x2f642a1f,0xaf64aa1f,0x2f642a1f,0xaf64aa1f,0x2f642a1f,0xaa1faf64,0x2a1f2f64,0xaa1faf64,0x2a1f2f64,
0xaf64ada8,0xaa1f2da8,0x2f642da8,0x2a1fada8,0x2a1f3000,0x2f648000,0xaa1fb000,0xaf640000,0x2a1fada8,0xaf64ada8,0xaa1f2da8,0x2f642da8,0xaf648000,0x2a1f3000,0x2f648000,0xaa1fb000,
0xac72afd9,0xaea7263e,0x2c722fd9,0x2ea7a63e,0xa63e2ea7,0x2fd92c72,0x263eaea7,0xafd9ac72,0x2ea7a63e,0xac72afd9,0xaea7263e,0x2c722fd9,0xafd9ac72,0xa63e2ea7,0x2fd92c72,0x263eaea7,
0xada8ada8,0xada8ada8,0xada8ada8,0xada8ada8,0x2da82da8,0x2da82da8,0x2da82da8,0x2da82da8,0xada82da8,0xada82da8,0xada82da8,0xada82da8,0x2da8ada8,0x2da8ada8,0x2da8ada8,0x2da8ada8,
0xb0008000,0xb0000000,0xb0000000,0xb0000000,0x30008000,0x30008000,0x30008000,0x30008000,0x3000,0x3000,0x3000,0x80003000,0x8000b000,0x8000b000,0x8000b000,0x8000b000,
0xac722fd9,0xaea7a63e,0x2c72afd9,0x2ea7263e,0xa63eaea7,0x2fd9ac72,0x263e2ea7,0xafd92c72,0x2ea7263e,0xac722fd9,0xaea7a63e,0x2c72afd9,0xafd92c72,0xa63eaea7,0x2fd9ac72,0x263e2ea7,
0x2a1f2da8,0xaf642da8,0xaa1fada8,0x2f64ada8,0xaf648000,0x2a1fb000,0x2f648000,0xaa1f3000,0x2f64ada8,0x2a1f2da8,0xaf642da8,0xaa1fada8,0xaa1f3000,0xaf640000,0x2a1fb000,0x2f648000,
0xaf642a1f,0x2f64aa1f,0xaf642a1f,0x2f64aa1f,0xaa1f2f64,0x2a1faf64,0xaa1f2f64,0x2a1faf64,0x2a1faf64,0xaa1f2f64,0x2a1faf64,0xaa1f2f64,0xaf642a1f,0x2f64aa1f,0xaf642a1f,0x2f64aa1f,
0xada83000,0x2da8b000,0xada83000,0x2da8b000,0x2da88000,0xada80000,0x2da88000,0xada88000,0xada88000,0x2da88000,0xada80000,0x2da88000,0xada83000,0x2da8b000,0xada83000,0x2da8b000,
0xafd92ea7,0xa63e2c72,0x2fd9aea7,0x263eac72,0xac72263e,0xaea72fd9,0x2c72a63e,0x2ea7afd9,0x263eac72,0xafd92ea7,0xa63e2c72,0x2fd9aea7,0x2ea7afd9,0xac72263e,0xaea72fd9,0x2c72a63e,
0xaa1f2da8,0x2f64ada8,0x2a1fada8,0xaf642da8,0xaf643000,0x2a1f8000,0x2f64b000,0xaa1f8000,0xaf642da8,0xaa1f2da8,0x2f64ada8,0x2a1fada8,0xaa1f8000,0xaf643000,0x2a1f8000,0x2f64b000,
0x80008000,0x80000000,0x80000000,0x0,0x80000000,0x80000000,0x80000000,0x80000000,0xb0003000,0xb0003000,0xb0003000,0xb0003000,0xb0003000,0xb0003000,0xb0003000,0xb0003000,
0x3000b000,0x3000b000,0x3000b000,0x3000b000,0x3000b000,0x3000b000,0x3000b000,0x3000b000,0x80000000,0x80000000,0x80008000,0x80008000,0x80000000,0x80008000,0x80008000,0x80008000,
0x2f64ada8,0x2a1fada8,0xaf642da8,0xaa1f2da8,0x2a1f8000,0x2f64b000,0xaa1f8000,0xaf643000,0xaa1f2da8,0x2f64ada8,0x2a1fada8,0xaf642da8,0xaf643000,0x2a1f0000,0x2f64b000,0xaa1f8000,
0x263eac72,0xafd92ea7,0xa63e2c72,0x2fd9aea7,0x2ea7afd9,0xac72263e,0xaea72fd9,0x2c72a63e,0x2fd9aea7,0x263eac72,0xafd92ea7,0xa63e2c72,0x2c72a63e,0x2ea7afd9,0xac72263e,0xaea72fd9,
0xada83000,0x2da8b000,0xada83000,0x2da8b000,0x2da80000,0xada88000,0x2da88000,0xada88000,0x2da88000,0xada88000,0x2da80000,0xada88000,0x2da8b000,0xada83000,0x2da8b000,0xada83000,
0x2f64aa1f,0xaf642a1f,0x2f64aa1f,0xaf642a1f,0x2a1faf64,0xaa1f2f64,0x2a1faf64,0xaa1f2f64,0x2a1faf64,0xaa1f2f64,0x2a1faf64,0xaa1f2f64,0xaf642a1f,0x2f64aa1f,0xaf642a1f,0x2f64aa1f,
0x2f64ada8,0x2a1f2da8,0xaf642da8,0xaa1fada8,0xaa1f3000,0xaf648000,0x2a1fb000,0x2f640000,0xaa1fada8,0x2f64ada8,0x2a1f2da8,0xaf642da8,0x2f648000,0xaa1f3000,0xaf648000,0x2a1fb000,
0xaea7a63e,0x2c72afd9,0x2ea7263e,0xac722fd9,0x2fd9ac72,0x263e2ea7,0xafd92c72,0xa63eaea7,0xac722fd9,0xaea7a63e,0x2c72afd9,0x2ea7263e,0xa63eaea7,0x2fd9ac72,0x263e2ea7,0xafd92c72,
0xada8ada8,0xada8ada8,0xada8ada8,0xada8ada8,0x2da82da8,0x2da82da8,0x2da82da8,0x2da82da8,0x2da8ada8,0x2da8ada8,0x2da8ada8,0x2da8ada8,0xada82da8,0xada82da8,0xada82da8,0xada82da8,
0x30008000,0x30000000,0x30000000,0x30000000,0xb0008000,0xb0008000,0xb0008000,0xb0000000,0x80003000,0x80003000,0x80003000,0x3000,0xb000,0x8000b000,0xb000,0xb000,
0x2ea7a63e,0xac72afd9,0xaea7263e,0x2c722fd9,0xafd9ac72,0xa63e2ea7,0x2fd92c72,0x263eaea7,0x2c722fd9,0x2ea7a63e,0xac72afd9,0xaea7263e,0x263eaea7,0xafd9ac72,0xa63e2ea7,0x2fd92c72,
0xaa1f2da8,0x2f642da8,0x2a1fada8,0xaf64ada8,0x2f648000,0xaa1fb000,0xaf640000,0x2a1f3000,0xaf64ada8,0xaa1f2da8,0x2f642da8,0x2a1fada8,0x2a1f3000,0x2f648000,0xaa1fb000,0xaf648000,
0xaa1faf64,0x2a1f2f64,0xaa1faf64,0x2a1f2f64,0x2f642a1f,0xaf64aa1f,0x2f642a1f,0xaf64aa1f,0xaf64aa1f,0x2f642a1f,0xaf64aa1f,0x2f642a1f,0xaa1faf64,0x2a1f2f64,0xaa1faf64,0x2a1f2f64,
0x2da83000,0xada8b000,0x2da83000,0xada8b000,0xada88000,0x2da88000,0xada88000,0x2da80000,0x2da88000,0xada88000,0x2da80000,0xada80000,0x2da83000,0xada8b000,0x2da83000,0xada8b000,
0xa63eac72,0x2fd92ea7,0x263e2c72,0xafd9aea7,0xaea7afd9,0x2c72263e,0x2ea72fd9,0xac72a63e,0xafd9aea7,0xa63eac72,0x2fd92ea7,0x263e2c72,0xac72a63e,0xaea7afd9,0x2c72263e,0x2ea72fd9,
0x2a1f2da8,0xaf64ada8,0xaa1fada8,0x2f642da8,0x2f643000,0xaa1f8000,0xaf64b000,0x2a1f0000,0x2f642da8,0x2a1f2da8,0xaf64ada8,0xaa1fada8,0x2a1f8000,0x2f643000,0xaa1f8000,0xaf64b000,
0x3c003c00,0x3c003c00,0x3c003c00,0x3c003c00,0x3c003c00,0x3c003c00,0x3c003c00,0x3c003c00,0x80008000,0x80008000,0x80008000,0x80008000,0x80008000,0x80008000,0x80008000,0x80008000,
0x3bd93c00,0x3aa73b64,0x387239a8,0x323e361f,0xb23e0000,0xb872b61f,0xbaa7b9a8,0xbbd9bb64,0xb23e8000,0xb872b61f,0xbaa7b9a8,0xbbd9bb64,0xbbd9bc00,0xbaa7bb64,0xb872b9a8,0xb23eb61f,
0xbb64bc00,0xb61fb9a8,0x361f8000,0x3b6439a8,0x3b643c00,0x361f39a8,0xb61f0000,0xbb64b9a8,0x361f8000,0x3b6439a8,0x3b643c00,0x361f39a8,0xb61f8000,0xbb64b9a8,0xbb64bc00,0xb61fb9a8,
0x38728000,0x3bd93b64,0x323e39a8,0xbaa7b61f,0x3aa73c00,0xb23e361f,0xbbd9b9a8,0xb872bb64,0x3aa73c00,0xb23e361f,0xbbd9b9a8,0xb872bb64,0xb8728000,0xbbd9bb64,0xb23eb9a8,0x3aa7361f,
0xbc008000,0x3c008000,0xbc000000,0x3c008000,0xbc000000,0x3c008000,0xbc000000,0x3c008000,0x3c00,0x8000bc00,0x3c00,0x8000bc00,0x3c00,0x8000bc00,0x80003c00,0x8000bc00,
0xbbd98000,0x3aa7361f,0xb872b9a8,0x323e3b64,0x323ebc00,0xb8723b64,0x3aa7b9a8,0xbbd9361f,0xb23e3c00,0x3872bb64,0xbaa739a8,0x3bd9b61f,0xbbd90000,0x3aa7361f,0xb872b9a8,0x323e3b64,
0x3b648000,0xb61fb9a8,0xb61f3c00,0x3b64b9a8,0xbb648000,0x361f39a8,0x361fbc00,0xbb6439a8,0x361fbc00,0xbb6439a8,0x3b648000,0xb61fb9a8,0xb61f3c00,0x3b64b9a8,0xbb640000,0x361f39a8,
0xb8723c00,0x3bd9b61f,0xb23eb9a8,0xbaa73b64,0xbaa78000,0xb23e3b64,0x3bd9b9a8,0xb872b61f,0x3aa78000,0x323ebb64,0xbbd939a8,0x3872361f,0xb8723c00,0x3bd9b61f,0xb23eb9a8,0xbaa73b64,
0xbbd93c00,0xbaa73b64,0xb87239a8,0xb23e361f,0x323e8000,0x3872b61f,0x3aa7b9a8,0x3bd9bb64,0x323e8000,0x3872b61f,0x3aa7b9a8,0x3bd9bb64,0x3bd9bc00,0x3aa7bb64,0x3872b9a8,0x323eb61f,
0xbc003c00,0xbc003c00,0xbc003c00,0xbc003c00,0xbc003c00,0xbc003c00,0xbc003c00,0xbc003c00,0x80008000,0x80000000,0x80000000,0x80000000,0x80000000,0x80000000,0x0,0x80000000,
0xb8728000,0xbbd93b64,0xb23e39a8,0x3aa7b61f,0xbaa73c00,0x323e361f,0x3bd9b9a8,0x3872bb64,0xbaa73c00,0x323e361f,0x3bd9b9a8,0x3872bb64,0x38728000,0x3bd9bb64,0x323eb9a8,0xbaa7361f,
0x3b64bc00,0x361fb9a8,0xb61f8000,0xbb6439a8,0xbb643c00,0xb61f39a8,0x361f0000,0x3b64b9a8,0xb61f8000,0xbb6439a8,0xbb643c00,0xb61f39a8,0x361f8000,0x3b64b9a8,0x3b64bc00,0x361fb9a8,
0x3bd98000,0xbaa7361f,0x3872b9a8,0xb23e3b64,0xb23ebc00,0x38723b64,0xbaa7b9a8,0x3bd9361f,0x323e3c00,0xb872bb64,0x3aa739a8,0xbbd9b61f,0x3bd98000,0xbaa7361f,0x3872b9a8,0xb23e3b64,
0x3c008000,0xbc008000,0x3c000000,0xbc008000,0x3c000000,0xbc008000,0x3c000000,0xbc000000,0x80003c00,0xbc00,0x80003c00,0x8000bc00,0x80003c00,0xbc00,0x80003c00,0xbc00,
0x38723c00,0xbbd9b61f,0x323eb9a8,0x3aa73b64,0x3aa78000,0x323e3b64,0xbbd9b9a8,0x3872b61f,0xbaa78000,0xb23ebb64,0x3bd939a8,0xb872361f,0x38723c00,0xbbd9b61f,0x323eb9a8,0x3aa73b64,
0xbb640000,0x361fb9a8,0x361f3c00,0xbb64b9a8,0x3b648000,0xb61f39a8,0xb61fbc00,0x3b6439a8,0xb61fbc00,0x3b6439a8,0xbb640000,0x361fb9a8,0x361f3c00,0xbb64b9a8,0x3b648000,0xb61f39a8,
0x39a83c00,0xb9a80000,0xb9a8bc00,0x39a88000,0x39a83c00,0xb9a80000,0xb9a8bc00,0x39a88000,0xb9a88000,0xb9a8bc00,0x39a88000,0x39a83c00,0xb9a80000,0xb9a8bc00,0x39a88000,0x39a83c00,
0x38723c00,0xbbd9b61f,0x323eb9a8,0x3aa73b64,0xbaa70000,0xb23ebb64,0x3bd939a8,0xb872361f,0xbaa78000,0xb23ebb64,0x3bd939a8,0xb872361f,0xb872bc00,0x3bd9361f,0xb23e39a8,0xbaa7bb64,
0xb61fbc00,0x3b6439a8,0xbb640000,0x361fb9a8,0x361f3c00,0xbb64b9a8,0x3b648000,0xb61f39a8,0x3b648000,0xb61f39a8,0xb61fbc00,0x3b6439a8,0xbb648000,0x361fb9a8,0x361f3c00,0xbb64b9a8,
0x3bd98000,0xbaa7361f,0x3872b9a8,0xb23e3b64,0x323e3c00,0xb872bb64,0x3aa739a8,0xbbd9b61f,0x323e3c00,0xb872bb64,0x3aa739a8,0xbbd9b61f,0xbbd98000,0x3aa7b61f,0xb87239a8,0x323ebb64,
0xb9a88000,0xb9a83c00,0x39a88000,0x39a8bc00,0xb9a80000,0xb9a83c00,0x39a88000,0x39a8bc00,0xb9a83c00,0x39a88000,0x39a8bc00,0xb9a80000,0xb9a83c00,0x39a88000,0x39a8bc00,0xb9a88000,
0xb8728000,0xbbd93b64,0xb23e39a8,0x3aa7b61f,0x3aa7bc00,0xb23eb61f,0xbbd939a8,0xb8723b64,0xbaa73c00,0x323e361f,0x3bd9b9a8,0x3872bb64,0xb8728000,0xbbd93b64,0xb23e39a8,0x3aa7b61f,
0x361f8000,0x3b64b9a8,0x3b64bc00,0x361fb9a8,0xb61f8000,0xbb6439a8,0xbb643c00,0xb61f39a8,0x3b64bc00,0x361fb9a8,0xb61f8000,0xbb6439a8,0xbb643c00,0xb61f39a8,0x361f8000,0x3b64b9a8,
0xbbd93c00,0xbaa73b64,0xb87239a8,0xb23e361f,0xb23e8000,0xb872361f,0xbaa739a8,0xbbd93b64,0x323e8000,0x3872b61f,0x3aa7b9a8,0x3bd9bb64,0xbbd93c00,0xbaa73b64,0xb87239a8,0xb23e361f,
0xb8723c00,0x3bd9b61f,0xb23eb9a8,0xbaa73b64,0x3aa78000,0x323ebb64,0xbbd939a8,0x3872361f,0x3aa78000,0x323ebb64,0xbbd939a8,0x3872361f,0x3872bc00,0xbbd9361f,0x323e39a8,0x3aa7bb64,
0xb9a83c00,0x39a80000,0x39a8bc00,0xb9a88000,0xb9a83c00,0x39a88000,0x39a8bc00,0xb9a88000,0x39a88000,0x39a8bc00,0xb9a88000,0xb9a83c00,0x39a80000,0x39a8bc00,0xb9a88000,0xb9a83c00,
0xbbd98000,0x3aa7361f,0xb872b9a8,0x323e3b64,0xb23e3c00,0x3872bb64,0xbaa739a8,0x3bd9b61f,0xb23e3c00,0x3872bb64,0xbaa739a8,0x3bd9b61f,0x3bd98000,0xbaa7b61f,0x387239a8,0xb23ebb64,
0x361fbc00,0xbb6439a8,0x3b640000,0xb61fb9a8,0xb61f3c00,0x3b64b9a8,0xbb648000,0x361f39a8,0xbb648000,0x361f39a8,0x361fbc00,0xbb6439a8,0x3b648000,0xb61fb9a8,0xb61f3c00,0x3b64b9a8,
0x38728000,0x3bd93b64,0x323e39a8,0xbaa7b61f,0xbaa7bc00,0x323eb61f,0x3bd939a8,0x38723b64,0x3aa73c00,0xb23e361f,0xbbd9b9a8,0xb872bb64,0x38728000,0x3bd93b64,0x323e39a8,0xbaa7b61f,
0x39a88000,0x39a83c00,0xb9a88000,0xb9a8bc00,0x39a80000,0x39a83c00,0xb9a80000,0xb9a8bc00,0x39a83c00,0xb9a88000,0xb9a8bc00,0x39a88000,0x39a83c00,0xb9a88000,0xb9a8bc00,0x39a80000,
0x3bd93c00,0x3aa73b64,0x387239a8,0x323e361f,0x323e8000,0x3872361f,0x3aa739a8,0x3bd93b64,0xb23e8000,0xb872b61f,0xbaa7b9a8,0xbbd9bb64,0x3bd93c00,0x3aa73b64,0x387239a8,0x323e361f,
0xb61f8000,0xbb64b9a8,0xbb64bc00,0xb61fb9a8,0x361f8000,0x3b6439a8,0x3b643c00,0x361f39a8,0xbb64bc00,0xb61fb9a8,0x361f0000,0x3b6439a8,0x3b643c00,0x361f39a8,0xb61f8000,0xbb64b9a8,
0x0,0x0,0x0,0x0,0x0,0x0,0x0,0x0,0x3c003c00,0x3c003c00,0x3c003c00,0x3c003c00,0x3c003c00,0x3c003c00,0x3c003c00,0x3c003c00,
0x323e0000,0x3872361f,0x3aa739a8,0x3bd93b64,0x3bd93c00,0x3aa73b64,0x387239a8,0x323e361f,0x3bd93c00,0x3aa73b64,0x387239a8,0x323e361f,0xb23e0000,0xb872b61f,0xbaa7b9a8,0xbbd9bb64,
0xb61f0000,0xbb64b9a8,0xbb64bc00,0xb61fb9a8,0x361f0000,0x3b6439a8,0x3b643c00,0x361f39a8,0xbb64bc00,0xb61fb9a8,0x361f8000,0x3b6439a8,0x3b643c00,0x361f39a8,0xb61f0000,0xbb64b9a8,
0xbaa7bc00,0x323eb61f,0x3bd939a8,0x38723b64,0x38720000,0x3bd93b64,0x323e39a8,0xbaa7b61f,0x38728000,0x3bd93b64,0x323e39a8,0xbaa7b61f,0x3aa73c00,0xb23e361f,0xbbd9b9a8,0xb872bb64,
0x3c00,0x8000bc00,0x3c00,0x8000bc00,0x3c00,0x8000bc00,0x80003c00,0x8000bc00,0x3c000000,0xbc000000,0x3c008000,0xbc000000,0x3c008000,0xbc000000,0x3c008000,0xbc000000,
0xb23e3c00,0x3872bb64,0xbaa739a8,0x3bd9b61f,0xbbd90000,0x3aa7361f,0xb872b9a8,0x323e3b64,0x3bd90000,0xbaa7b61f,0x387239a8,0xb23ebb64,0xb23e3c00,0x3872bb64,0xbaa739a8,0x3bd9b61f,
0x361fbc00,0xbb6439a8,0x3b648000,0xb61fb9a8,0xb61f3c00,0x3b64b9a8,0xbb640000,0x361f39a8,0xbb640000,0x361f39a8,0x361fbc00,0xbb6439a8,0x3b640000,0xb61fb9a8,0xb61f3c00,0x3b64b9a8,
0x3aa78000,0x323ebb64,0xbbd939a8,0x3872361f,0xb8723c00,0x3bd9b61f,0xb23eb9a8,0xbaa73b64,0x3872bc00,0xbbd9361f,0x323e39a8,0x3aa7bb64,0x3aa70000,0x323ebb64,0xbbd939a8,0x3872361f,
0xb23e0000,0xb872361f,0xbaa739a8,0xbbd93b64,0xbbd93c00,0xbaa73b64,0xb87239a8,0xb23e361f,0xbbd93c00,0xbaa73b64,0xb87239a8,0xb23e361f,0x323e8000,0x3872b61f,0x3aa7b9a8,0x3bd9bb64,
0x0,0x8000,0x8000,0x8000,0x8000,0x8000,0x80008000,0x8000,0xbc003c00,0xbc003c00,0xbc003c00,0xbc003c00,0xbc003c00,0xbc003c00,0xbc003c00,0xbc003c00,
0x3aa7bc00,0xb23eb61f,0xbbd939a8,0xb8723b64,0xb8720000,0xbbd93b64,0xb23e39a8,0x3aa7b61f,0xb8728000,0xbbd93b64,0xb23e39a8,0x3aa7b61f,0xbaa73c00,0x323e361f,0x3bd9b9a8,0x3872bb64,
0x361f0000,0x3b64b9a8,0x3b64bc00,0x361fb9a8,0xb61f0000,0xbb6439a8,0xbb643c00,0xb61f39a8,0x3b64bc00,0x361fb9a8,0xb61f8000,0xbb6439a8,0xbb643c00,0xb61f39a8,0x361f0000,0x3b64b9a8,
0x323e3c00,0xb872bb64,0x3aa739a8,0xbbd9b61f,0x3bd98000,0xbaa7361f,0x3872b9a8,0xb23e3b64,0xbbd90000,0x3aa7b61f,0xb87239a8,0x323ebb64,0x323e3c00,0xb872bb64,0x3aa739a8,0xbbd9b61f,
0x80003c00,0xbc00,0x80003c00,0x8000bc00,0x80003c00,0xbc00,0x80003c00,0xbc00,0xbc000000,0x3c000000,0xbc008000,0x3c000000,0xbc008000,0x3c000000,0xbc008000,0x3c008000,
0xbaa78000,0xb23ebb64,0x3bd939a8,0xb872361f,0x38723c00,0xbbd9b61f,0x323eb9a8,0x3aa73b64,0xb872bc00,0x3bd9361f,0xb23e39a8,0xbaa7bb64,0xbaa70000,0xb23ebb64,0x3bd939a8,0xb872361f,
0xb61fbc00,0x3b6439a8,0xbb640000,0x361fb9a8,0x361f3c00,0xbb64b9a8,0x3b648000,0xb61f39a8,0x3b648000,0xb61f39a8,0xb61fbc00,0x3b6439a8,0xbb640000,0x361fb9a8,0x361f3c00,0xbb64b9a8,
0x39a80000,0x39a83c00,0xb9a80000,0xb9a8bc00,0x39a88000,0x39a83c00,0xb9a80000,0xb9a8bc00,0x39a83c00,0xb9a80000,0xb9a8bc00,0x39a88000,0x39a83c00,0xb9a80000,0xb9a8bc00,0x39a88000,
0x3aa70000,0x323e3b64,0xbbd9b9a8,0x3872b61f,0x38723c00,0xbbd9b61f,0x323eb9a8,0x3aa73b64,0x38723c00,0xbbd9b61f,0x323eb9a8,0x3aa73b64,0xbaa70000,0xb23ebb64,0x3bd939a8,0xb872361f,
0xbb640000,0x361fb9a8,0x361f3c00,0xbb64b9a8,0x3b640000,0xb61f39a8,0xb61fbc00,0x3b6439a8,0xb61fbc00,0x3b6439a8,0xbb640000,0x361fb9a8,0x361f3c00,0xbb64b9a8,0x3b648000,0xb61f39a8,
0xb23ebc00,0x38723b64,0xbaa7b9a8,0x3bd9361f,0x3bd90000,0xbaa7361f,0x3872b9a8,0xb23e3b64,0x3bd98000,0xbaa7361f,0x3872b9a8,0xb23e3b64,0x323e3c00,0xb872bb64,0x3aa739a8,0xbbd9b61f,
0xb9a83c00,0x39a88000,0x39a8bc00,0xb9a80000,0xb9a83c00,0x39a88000,0x39a8bc00,0xb9a88000,0x39a80000,0x39a8bc00,0xb9a80000,0xb9a83c00,0x39a88000,0x39a8bc00,0xb9a80000,0xb9a83c00,
0xbaa73c00,0x323e361f,0x3bd9b9a8,0x3872bb64,0xb8728000,0xbbd93b64,0xb23e39a8,0x3aa7b61f,0x38720000,0x3bd9bb64,0x323eb9a8,0xbaa7361f,0xbaa73c00,0x323e361f,0x3bd9b9a8,0x3872bb64,
0x3b64bc00,0x361fb9a8,0xb61f8000,0xbb6439a8,0xbb643c00,0xb61f39a8,0x361f8000,0x3b64b9a8,0xb61f0000,0xbb6439a8,0xbb643c00,0xb61f39a8,0x361f0000,0x3b64b9a8,0x3b64bc00,0x361fb9a8,
0x323e8000,0x3872b61f,0x3aa7b9a8,0x3bd9bb64,0xbbd93c00,0xbaa73b64,0xb87239a8,0xb23e361f,0x3bd9bc00,0x3aa7bb64,0x3872b9a8,0x323eb61f,0x323e0000,0x3872b61f,0x3aa7b9a8,0x3bd9bb64,
0xbaa70000,0xb23e3b64,0x3bd9b9a8,0xb872b61f,0xb8723c00,0x3bd9b61f,0xb23eb9a8,0xbaa73b64,0xb8723c00,0x3bd9b61f,0xb23eb9a8,0xbaa73b64,0x3aa78000,0x323ebb64,0xbbd939a8,0x3872361f,
0xb9a80000,0xb9a83c00,0x39a80000,0x39a8bc00,0xb9a88000,0xb9a83c00,0x39a80000,0x39a8bc00,0xb9a83c00,0x39a80000,0x39a8bc00,0xb9a88000,0xb9a83c00,0x39a88000,0x39a8bc00,0xb9a88000,
0x323ebc00,0xb8723b64,0x3aa7b9a8,0xbbd9361f,0xbbd90000,0x3aa7361f,0xb872b9a8,0x323e3b64,0xbbd98000,0x3aa7361f,0xb872b9a8,0x323e3b64,0xb23e3c00,0x3872bb64,0xbaa739a8,0x3bd9b61f,
0x3b640000,0xb61fb9a8,0xb61f3c00,0x3b64b9a8,0xbb640000,0x361f39a8,0x361fbc00,0xbb6439a8,0x361fbc00,0xbb6439a8,0x3b640000,0xb61fb9a8,0xb61f3c00,0x3b64b9a8,0xbb648000,0x361f39a8,
0x3aa73c00,0xb23e361f,0xbbd9b9a8,0xb872bb64,0x38728000,0x3bd93b64,0x323e39a8,0xbaa7b61f,0xb8720000,0xbbd9bb64,0xb23eb9a8,0x3aa7361f,0x3aa73c00,0xb23e361f,0xbbd9b9a8,0xb872bb64,
0x39a83c00,0xb9a88000,0xb9a8bc00,0x39a88000,0x39a83c00,0xb9a88000,0xb9a8bc00,0x39a80000,0xb9a80000,0xb9a8bc00,0x39a80000,0x39a83c00,0xb9a88000,0xb9a8bc00,0x39a88000,0x39a83c00,
0xb23e8000,0xb872b61f,0xbaa7b9a8,0xbbd9bb64,0x3bd93c00,0x3aa73b64,0x387239a8,0x323e361f,0xbbd9bc00,0xbaa7bb64,0xb872b9a8,0xb23eb61f,0xb23e0000,0xb872b61f,0xbaa7b9a8,0xbbd9bb64,
0xbb64bc00,0xb61fb9a8,0x361f0000,0x3b6439a8,0x3b643c00,0x361f39a8,0xb61f8000,0xbb64b9a8,0x361f0000,0x3b6439a8,0x3b643c00,0x361f39a8,0xb61f0000,0xbb64b9a8,0xbb64bc00,0xb61fb9a8,
};
__device__ __align__(1024) bf16 g_x1T[DM * XP];
__device__ __align__(1024) bf16 g_x2T[DM * XP];
__device__ __align__(1024) unsigned g_xcnt[10][4][32];
__device__ __align__(1024) uint4 g_of[8][16][1280];
__device__ __align__(1024) float g_fs[2][SEQ];

#define TS_SMEM 0
#define TS_DECL
#define TS_ARG
#define TS_PASS
#define TS_PHASE(p)
#define TS(i)
#define TSX(row, i)
#define TS_BEGIN
#define TS_END

struct cplx { float r, i; };
__device__ __forceinline__ cplx cmul(cplx a, cplx b) {
    cplx o;
    o.r = fmaf(a.r, b.r, -a.i * b.i);
    o.i = fmaf(a.r, b.i, a.i * b.r);
    return o;
}
__device__ __forceinline__ cplx csq(cplx a) {
    cplx o;
    o.r = fmaf(a.r, a.r, -a.i * a.i);
    o.i = 2.f * a.r * a.i;
    return o;
}
__device__ __forceinline__ cplx cexp_p(float arl, float ai, float p) {
    float mag = ex2(arl * p);
    float ang = ai * p;
    float n = rintf(ang * 0.15915494309189535f);
    float r = fmaf(n, -6.2831854820251465f, ang);
    r = fmaf(n, 1.7484555e-7f, r);
    cplx o;
    o.r = mag * __cosf(r);
    o.i = mag * __sinf(r);
    return o;
}

__device__ __forceinline__ uint32_t pack2h(float lo, float hi) {
    uint32_t r;
    asm("cvt.rn.f16x2.f32 %0, %1, %2;" : "=r"(r) : "f"(hi), "f"(lo));
    return r;
}
__device__ __forceinline__ uint32_t hmul(uint32_t a, uint32_t b) { uint32_t d; asm("mul.rn.f16x2 %0, %1, %2;" : "=r"(d) : "r"(a), "r"(b)); return d; }
__device__ __forceinline__ uint32_t hfma(uint32_t a, uint32_t b, uint32_t c) { uint32_t d; asm("fma.rn.f16x2 %0, %1, %2, %3;" : "=r"(d) : "r"(a), "r"(b), "r"(c)); return d; }
__device__ __forceinline__ uint32_t hfms(uint32_t a, uint32_t b, uint32_t c) {
    uint32_t d;
    asm("{\n.reg .b32 n;\nneg.f16x2 n, %1;\nfma.rn.f16x2 %0, n, %2, %3;\n}" : "=r"(d) : "r"(a), "r"(b), "r"(c));
    return d;
}
__device__ __forceinline__ uint32_t hadd(uint32_t a, uint32_t b) { uint32_t d; asm("add.rn.f16x2 %0, %1, %2;" : "=r"(d) : "r"(a), "r"(b)); return d; }
__device__ __forceinline__ uint32_t hsub(uint32_t a, uint32_t b) { uint32_t d; asm("sub.rn.f16x2 %0, %1, %2;" : "=r"(d) : "r"(a), "r"(b)); return d; }
__device__ __forceinline__ uint4 ldg_tab(int tab, int t) { return ldg128((const uint4*)c_fft + t + tab * 128); }
__device__ __forceinline__ uint32_t u4(const uint4& v, int i) { return i == 0 ? v.x : i == 1 ? v.y : i == 2 ? v.z : v.w; }
struct cpair { uint32_t r, i; };
__device__ __forceinline__ cpair pmul(cpair p, uint32_t z) {
    const __half2 zv = *reinterpret_cast<const __half2*>(&z), pr = *reinterpret_cast<const __half2*>(&p.r), pi = *reinterpret_cast<const __half2*>(&p.i);
    const __half2 zr = __low2half2(zv), zi = __high2half2(zv);
    const __half2 a = __hfma2(__hneg2(pi), zi, __hmul2(pr, zr)), b = __hfma2(pi, zr, __hmul2(pr, zi));
    return {*reinterpret_cast<const uint32_t*>(&a), *reinterpret_cast<const uint32_t*>(&b)};
}
__device__ __forceinline__ uint32_t packz(cplx z) { return pack2h(z.r, z.i); }
__device__ __forceinline__ void wgmma_kg(float (&d)[24], uint64_t da, uint64_t db, int scale_d) {
    asm volatile("{\n.reg .pred p;\nsetp.ne.b32 p, %26, 0;\n"
                 "wgmma.mma_async.sync.aligned.m64n48k16.f32.f16.f16 "
                 "{%0,%1,%2,%3,%4,%5,%6,%7,%8,%9,%10,%11,%12,%13,%14,%15,%16,%17,%18,%19,%20,%21,%22,%23}, %24, %25, p, 1, 1, 1, 1;\n}\n"
                 : "+f"(d[0]), "+f"(d[1]), "+f"(d[2]), "+f"(d[3]), "+f"(d[4]), "+f"(d[5]), "+f"(d[6]), "+f"(d[7]), "+f"(d[8]), "+f"(d[9]),
                   "+f"(d[10]), "+f"(d[11]), "+f"(d[12]), "+f"(d[13]), "+f"(d[14]), "+f"(d[15]), "+f"(d[16]), "+f"(d[17]), "+f"(d[18]), "+f"(d[19]),
                   "+f"(d[20]), "+f"(d[21]), "+f"(d[22]), "+f"(d[23])
                 : "l"(da), "l"(db), "r"(scale_d));
}

struct SsmParams { const bf16 *lar, *aim, *cre, *cim, *logdt, *dskip; const unsigned* epoch; };
constexpr int KG_TABLES = 6 * 16384, KG_RES = 1664;
struct KgShared { uint32_t kmax[6], kexp[6]; float cinv[6], tap0[6]; };
#define KS(f, i) (ks + (uint32_t)offsetof(KgShared, f) + 4 * (i))
struct KgParams { uint32_t l[3], a[3], r[3], i[3], dt, ds; };

__device__ __forceinline__ int cta_channel(int bx, int i) { return i < 2 ? 2 * bx + i : i < 4 ? 382 + 2 * bx + i : 256 + bx; }
__device__ __forceinline__ bool kg_is_hi(int warp) { return ((warp >> 1) ^ (warp >> 2)) & 1; }
__device__ __forceinline__ void kgen_load(KgParams& kp, int bx, int warp, int lane, const SsmParams& sp) {
    const int d = cta_channel(bx, 2 * (warp >> 2) + (warp & 1)), idx = d * (NMODE / 2) + lane;
    const bf16 *pr = kg_is_hi(warp) ? sp.cre : sp.lar, *pi = kg_is_hi(warp) ? sp.cim : sp.aim;
    kp.dt = __ldg((const uint16_t*)sp.logdt + d);
#pragma unroll
    for (int j = 0; j < 3; j++) {
        kp.l[j] = __ldg((const uint32_t*)sp.lar + idx + 32 * j); kp.a[j] = __ldg((const uint32_t*)sp.aim + idx + 32 * j);
        kp.r[j] = __ldg((const uint32_t*)pr + idx + 32 * j); kp.i[j] = __ldg((const uint32_t*)pi + idx + 32 * j);
    }
    kp.ds = __ldg((const uint16_t*)sp.dskip + cta_channel(bx, warp >> 1));
}

struct KgAnchors { uint32_t v[8]; };
__device__ __forceinline__ KgAnchors kg_anchor_lo(const KgParams& kp, uint32_t sel, float dt) {
    auto B = [&](uint32_t v) { return __uint_as_float(__byte_perm(v, 0u, sel)); };
    const float arl = -rbf(ex2(B(kp.l[0]) * 1.4426950408889634f)) * dt * 1.4426950408889634f, ai = B(kp.a[0]) * dt;
    const cplx z8 = cexp_p(arl, ai, 8.f), z16 = csq(z8), z24 = cmul(z16, z8), z32 = csq(z16), z64 = csq(z32), z128 = csq(z64), z192 = cmul(z128, z64);
    return {{pack2h(1.f, z8.r), pack2h(0.f, z8.i), pack2h(z16.r, z24.r), pack2h(z16.i, z24.i), packz(z32), packz(z64), packz(z128), packz(z192)}};
}
__device__ __forceinline__ KgAnchors kg_anchor_hi(const KgParams& kp, uint32_t sel, float dt, float cs) {
    auto B = [&](uint32_t v) { return __uint_as_float(__byte_perm(v, 0u, sel)); };
    const float arl = -rbf(ex2(B(kp.l[0]) * 1.4426950408889634f)) * dt * 1.4426950408889634f, ai = B(kp.a[0]) * dt;
    const cplx z1 = cexp_p(arl, -ai, 1.f), z2 = csq(z1), z4 = csq(z2), z256 = cexp_p(arl, -ai, 256.f), z512 = csq(z256), z1024 = csq(z512);
    const cplx H0 = {B(kp.r[0]) * cs, -B(kp.i[0]) * cs}, H4 = cmul(H0, z4);
    return {{pack2h(H0.r, H4.r), pack2h(H0.i, H4.i), packz(z1), packz(z2), packz(z256), packz(z512), packz(z1024), 0u}};
}

template <class Idle>
__device__ __forceinline__ void kgen_tables(KgParams& kp, uint32_t scr, uint32_t dump, uint32_t ks, int warp, int lane, Idle idle TS_ARG) {
    const int wg = warp >> 2, half = warp & 1, sw = lane & 7;
    const bool hi = kg_is_hi(warp);
    TS(23);
    const float dt = rbf(ex2(bf_lo(kp.dt) * 1.4426950408889634f));
    uint32_t sel = (wg == 2 && half) ? 0x3244u : 0x1044u;
    float cs = 0.f;
    KgAnchors an;
    if (hi) {
        uint32_t m = 0;
#pragma unroll
        for (int j = 0; j < 3; j++) m = __vmaxu2(m, __vmaxu2(kp.r[j] & 0x7FFF7FFFu, kp.i[j] & 0x7FFF7FFFu));
        m = __reduce_max_sync(~0u, max(m << 16, m & 0xFFFF0000u));
        const uint32_t e = min(max(__float_as_uint(2.f * dt * __uint_as_float(m)) >> 23, 2u), 252u);
        cs = 2.f * dt * __uint_as_float((253u - e) << 23);
        if (lane == 0) { sts32(KS(cinv, 2 * wg + half), (e + 1u) << 23); sts32(KS(kmax, 2 * wg + half), 0u); }
        an = kg_anchor_hi(kp, sel, dt, cs);
    } else {
        an = kg_anchor_lo(kp, sel, dt);
    }
    float acc[24];
#pragma unroll
    for (int i = 0; i < 24; i++) acc[i] = 0.f;
    uint32_t tb = scr + 2 * wg * 16384 + lane * 128;
    uint64_t da = mkdesc(scr + 2 * wg * 16384, 4096, 1024, 1);
    int flip = 16384;
#pragma unroll 1
    for (int c = wg == 2 ? 1 : 0, step = wg == 2 ? 2 : 1; c < 6; c += step) {
        if (wg < 2) sel ^= 0x2200u;
        if (!hi) {
            if (c & 1) { kp.l[0] = kp.l[1]; kp.l[1] = kp.l[2]; kp.a[0] = kp.a[1]; kp.a[1] = kp.a[2]; }
            cpair p[4];
            p[0] = {an.v[0], an.v[1]}; p[1] = {an.v[2], an.v[3]};
            p[2] = pmul(p[0], an.v[4]); p[3] = pmul(p[1], an.v[4]);
#pragma unroll
            for (int j = 0; j < 4; j++) {
                cpair v[4];
#pragma unroll
                for (int i = 0; i < 4; i++) v[i] = j ? pmul(p[i], an.v[4 + j]) : p[i];
                const uint32_t a = tb + (((4 * half + j) ^ sw) << 4);
                sts128(a, make_uint4(v[0].r, v[1].r, v[2].r, v[3].r));
                sts128(a + 4096, make_uint4(v[0].i, v[1].i, v[2].i, v[3].i));
            }
            an = kg_anchor_lo(kp, sel, dt);
        } else {
            if (c & 1) {
#pragma unroll
                for (int j = 0; j < 2; j++) { kp.l[j] = kp.l[j + 1]; kp.a[j] = kp.a[j + 1]; kp.r[j] = kp.r[j + 1]; kp.i[j] = kp.i[j + 1]; }
            }
            const uint32_t h1 = an.v[2], h2 = an.v[3], h256 = an.v[4], h512 = an.v[5], h1024 = an.v[6];
            cpair p[11];
            p[0] = {an.v[0], an.v[1]};
            p[1] = pmul(p[0], h2); p[2] = pmul(p[0], h1); p[3] = pmul(p[1], h1);
            p[4] = pmul(p[0], h256); p[5] = pmul(p[1], h256); p[6] = pmul(p[0], h512); p[7] = pmul(p[4], h512);
            p[8] = pmul({__byte_perm(p[0].r, p[4].r, 0x5410), __byte_perm(p[0].i, p[4].i, 0x5410)}, h1024);
            p[9] = pmul(p[8], h512); p[10] = pmul(p[8], h1024);
#pragma unroll
            for (int j = 0; j < 3; j++) {
                const uint32_t a = tb + 8192 + (((3 * half + j) ^ sw) << 4);
                sts128(a, make_uint4(p[4 * j].r, p[4 * j + 1].r, p[4 * j + 2].r, p[j < 2 ? 4 * j + 3 : 10].r));
                sts128(a + 4096, make_uint4(p[4 * j].i, p[4 * j + 1].i, p[4 * j + 2].i, p[j < 2 ? 4 * j + 3 : 10].i));
            }
            an = kg_anchor_hi(kp, sel, dt, cs);
        }
        if (c == 0) TS(24);
        if (c == 3) TS(25);
        fence_async_smem();
        wg_wait<0>();
        named_bar(5 + wg, 128);
        wg_fence();
#pragma unroll
        for (int k = 0; k < 4; k++) wgmma_kg(acc, da + k * 128, da + 512 + k * 128, 1);
        wg_commit();
        tb += flip; da += flip >> 4; flip = -flip;
    }
    const bool up = warp & 2;
    const int r = 2 * wg + up, lo0 = 16 * half + (lane >> 2);
    const uint32_t o = dump + r * KG_RES + lo0 * 52 + 4 * (lane & 3);
    const float ci = __uint_as_float(lds32(KS(cinv, r)));
    const float ds = warp <= 8 ? bf_lo(kp.ds) : 0.f;
    TS(26);
    idle();
    wg_wait<0>();
    float v[12], m = 0.f;
#pragma unroll
    for (int j = 0; j < 12; j++) { v[j] = up ? acc[12 + j] : acc[j]; m = fmaxf(m, fabsf(v[j])); }
#pragma unroll
    for (int j = 0; j < 6; j++) sts32(o + (j & 1) * 416 + (j >> 1) * 16, pack2h(v[2 * j], v[2 * j + 1]));
    const uint32_t mm = __reduce_max_sync(~0u, __float_as_uint(m));
    if (lane == 0) {
        asm volatile("red.shared.max.u32 [%0], %1;" ::"r"(KS(kmax, r)), "r"(mm) : "memory");
        if (!half) sts32(KS(tap0, r), __float_as_uint(fmaf(ci, v[0], ds)));
    }
}
#define F_STAG 4
__device__ __forceinline__ void wgmma_h64_rs(uint32_t (&d)[16], const uint4& a, uint64_t db, int scale_d) {
    asm volatile("{\n.reg .pred p;\nsetp.ne.b32 p, %21, 0;\n"
                 "wgmma.mma_async.sync.aligned.m64n64k16.f16.f16.f16 {%0,%1,%2,%3,%4,%5,%6,%7,%8,%9,%10,%11,%12,%13,%14,%15}, {%16,%17,%18,%19}, %20, p, 1, 1, 1;\n}\n"
                 : "+r"(d[0]), "+r"(d[1]), "+r"(d[2]), "+r"(d[3]), "+r"(d[4]), "+r"(d[5]), "+r"(d[6]), "+r"(d[7]), "+r"(d[8]), "+r"(d[9]),
                   "+r"(d[10]), "+r"(d[11]), "+r"(d[12]), "+r"(d[13]), "+r"(d[14]), "+r"(d[15])
                 : "r"(a.x), "r"(a.y), "r"(a.z), "r"(a.w), "l"(db), "r"(scale_d));
}
template <int TB>
__device__ __forceinline__ void wgmma_h32_rs(uint32_t (&d)[8], const uint4& a, uint64_t db, int scale_d) {
    asm volatile("{\n.reg .pred p;\nsetp.ne.b32 p, %13, 0;\n"
                 "wgmma.mma_async.sync.aligned.m64n32k16.f16.f16.f16 {%0,%1,%2,%3,%4,%5,%6,%7}, {%8,%9,%10,%11}, %12, p, 1, 1, %14;\n}\n"
                 : "+r"(d[0]), "+r"(d[1]), "+r"(d[2]), "+r"(d[3]), "+r"(d[4]), "+r"(d[5]), "+r"(d[6]), "+r"(d[7])
                 : "r"(a.x), "r"(a.y), "r"(a.z), "r"(a.w), "l"(db), "r"(scale_d), "n"(TB));
}
__device__ __forceinline__ void wgmma_s1(uint32_t (&d)[16], const uint4& a, uint64_t db, int scale_d) { wgmma_h64_rs(d, a, db, scale_d); }
__device__ __forceinline__ void wgmma_s1(uint32_t (&d)[8], const uint4& a, uint64_t db, int scale_d) { wgmma_h32_rs<1>(d, a, db, scale_d); }
__device__ __forceinline__ void wgmma_s4(float (&d)[32], const uint4& a, uint64_t db, uint32_t meta, int scale_d) {
    asm volatile("{\n.reg .pred p;\nsetp.ne.b32 p, %38, 0;\n"
                 "wgmma.mma_async.sp.sync.aligned.m64n64k32.f32.f16.f16 {%0,%1,%2,%3,%4,%5,%6,%7,%8,%9,%10,%11,%12,%13,%14,%15,%16,%17,%18,%19,%20,%21,%22,%23,%24,%25,%26,%27,%28,%29,%30,%31}, {%32,%33,%34,%35}, %36, %37, 0, p, 1, 1, 1;\n}\n"
                 : "+f"(d[0]), "+f"(d[1]), "+f"(d[2]), "+f"(d[3]), "+f"(d[4]), "+f"(d[5]), "+f"(d[6]), "+f"(d[7]), "+f"(d[8]), "+f"(d[9]), "+f"(d[10]), "+f"(d[11]), "+f"(d[12]), "+f"(d[13]), "+f"(d[14]), "+f"(d[15]), "+f"(d[16]), "+f"(d[17]), "+f"(d[18]), "+f"(d[19]), "+f"(d[20]), "+f"(d[21]), "+f"(d[22]), "+f"(d[23]), "+f"(d[24]), "+f"(d[25]), "+f"(d[26]), "+f"(d[27]), "+f"(d[28]), "+f"(d[29]), "+f"(d[30]), "+f"(d[31])
                 : "r"(a.x), "r"(a.y), "r"(a.z), "r"(a.w), "l"(db), "r"(meta), "r"(scale_d));
}
__device__ __forceinline__ void wgmma_s4(float (&d)[16], const uint4& a, uint64_t db, uint32_t meta, int scale_d) {
    asm volatile("{\n.reg .pred p;\nsetp.ne.b32 p, %22, 0;\n"
                 "wgmma.mma_async.sp.sync.aligned.m64n32k32.f32.f16.f16 {%0,%1,%2,%3,%4,%5,%6,%7,%8,%9,%10,%11,%12,%13,%14,%15}, {%16,%17,%18,%19}, %20, %21, 0, p, 1, 1, 1;\n}\n"
                 : "+f"(d[0]), "+f"(d[1]), "+f"(d[2]), "+f"(d[3]), "+f"(d[4]), "+f"(d[5]), "+f"(d[6]), "+f"(d[7]), "+f"(d[8]), "+f"(d[9]), "+f"(d[10]), "+f"(d[11]), "+f"(d[12]), "+f"(d[13]), "+f"(d[14]), "+f"(d[15])
                 : "r"(a.x), "r"(a.y), "r"(a.z), "r"(a.w), "l"(db), "r"(meta), "r"(scale_d));
}

__device__ __forceinline__ uint32_t& u4r(uint4& v, int i) { return i == 0 ? v.x : i == 1 ? v.y : i == 2 ? v.z : v.w; }

template <int NC>
__device__ __forceinline__ void fft_stage(const uint32_t (&u)[2][4], int c, uint32_t eo, int w, int lane) {
    const int mi = lane >> 3, mj = lane & 7;
    const uint32_t a = eo + (8 * w + mj) * 128 + (((4 * c + mi) ^ mj) << 4);
    stsm_x4(a, hadd(u[0][0], u[1][0]), hadd(u[0][1], u[1][1]), hadd(u[0][2], u[1][2]), hadd(u[0][3], u[1][3]));
    stsm_x4(NC == 2 ? a + 4096 : a ^ 64, hsub(u[0][0], u[1][0]), hsub(u[0][1], u[1][1]), hsub(u[0][2], u[1][2]), hsub(u[0][3], u[1][3]));
}
template <int NC>
__device__ __forceinline__ void kernel_stage(const uint4 (&ko)[2], uint32_t kt, uint32_t ks, int r, uint32_t eo, int w, int lane) {
    uint32_t u[2][2][4], sc[NC], t0[NC];
#pragma unroll
    for (int c = 0; c < NC; c++) {
        auto L = [](uint32_t a) { return __uint_as_float(lds32(a)); };
        const float ci = L(KS(cinv, r + c)), k0 = L(KS(tap0, r + c)) + (NC == 1 ? L(KS(tap0, r + 1)) : 0.f);
        const float mx = fmaxf(ci * (L(KS(kmax, r + c)) + (NC == 1 ? L(KS(kmax, r + 1)) : 0.f) + 0x1p-14f), fabsf(k0));
        const uint32_t e = min(max(__float_as_uint(mx) >> 23, 4u), 250u);
        const float s = __uint_as_float((253u - e) << 23), f = s * ci;
        if (w == 0 && lane == 0) sts32(KS(kexp, r + c), e);
        sc[c] = pack2h(f, f); t0[c] = pack2h(k0 * s, 0.f);
    }
#pragma unroll
    for (int h = 0; h < 2; h++)
#pragma unroll
        for (int j = 0; j < 4; j++) {
            const uint32_t a0 = kt + (u4(ko[h], j) & 0xFFFF), a1 = kt + (u4(ko[h], j) >> 16);
#pragma unroll
            for (int c = 0; c < 2; c++)
                asm volatile("{\n.reg .b16 a, b;\nld.shared.b16 a, [%1];\nld.shared.b16 b, [%2];\nmov.b32 %0, {a, b};\n}"
                             : "=r"(u[c][h][j]) : "r"(a0 + c * KG_RES), "r"(a1 + c * KG_RES) : "memory");
            if (NC == 1) u[0][h][j] = hadd(u[0][h][j], u[1][h][j]);
#pragma unroll
            for (int c = 0; c < NC; c++) {
                u[c][h][j] = hmul(u[c][h][j], sc[c]);
                if (h + j == 0 && w == 0 && lane == 0) u[c][0][0] = __byte_perm(t0[c], u[c][0][0], 0x7610);
            }
        }
#pragma unroll
    for (int c = 0; c < NC; c++) fft_stage<NC>(u[c], c, eo, w, lane);
}

template <int NC, bool SHEAR, class Mid>
__device__ __forceinline__ void fft_forward(const uint4 (&a1)[4], const uint4 (&tw)[4], uint32_t eo, uint32_t s2, uint32_t (&X)[NC][2][8], Mid mid) {
    uint32_t dr[8 * NC], di[8 * NC];
    const uint64_t de = mkdesc(eo, 4096, 1024, 1), d2 = mkdesc(s2, 16, 1024, 1);
    wg_fence();
    wgmma_s1(dr, a1[0], de, 0);
    wgmma_s1(di, a1[2], de + (NC == 2 ? 256 : 4), 0);
    wgmma_s1(dr, a1[1], de + 128, 1);
    wgmma_s1(di, a1[3], de + (NC == 2 ? 384 : 132), 1);
    wg_commit();
    mid();
    wg_wait<0>();
#pragma unroll
    for (int c = 0; c < NC; c++) {
        uint4 zr[2], zi[2];
#pragma unroll
        for (int p = 0; p < 2; p++)
#pragma unroll
            for (int i = 0; i < 4; i++) {
                const uint32_t r = dr[8 * c + 4 * p + i], m = di[8 * c + 4 * p + i], tr = u4(tw[p], i), ti = u4(tw[2 + p], i);
                if (SHEAR) {
                    const uint32_t r1 = hfma(tr, m, r), m1 = hfma(ti, r1, m);
                    u4r(zr[p], i) = hfma(tr, m1, r1); u4r(zi[p], i) = m1;
                } else {
                    u4r(zr[p], i) = hfms(m, ti, hmul(r, tr));
                    u4r(zi[p], i) = hfma(m, tr, hmul(r, ti));
                }
            }
        wg_fence();
        wgmma_h32_rs<0>(X[c][0], zi[0], d2 + 2, 0);
        wgmma_h32_rs<0>(X[c][1], zi[1], d2 + 6, 0);
        wgmma_h32_rs<0>(X[c][0], zr[0], d2, 1);
        wgmma_h32_rs<0>(X[c][1], zr[1], d2 + 4, 1);
        wg_commit();
    }
}

template <int NC, class Idle, class Staged>
__device__ __forceinline__ void conv_wg(int ch0, int layer, uint32_t eo, uint32_t zb, uint32_t s23, uint32_t kexp, uint32_t epoch, uint32_t st, uint32_t sbar, uint32_t fbar,
                                        int warp, int lane, uint4 (&a1)[4], uint4 (&tw)[4], Idle idle, Staged staged TS_ARG) {
    const int wg = warp >> 2, w = warp & 3, t = 32 * w + lane, mi = lane >> 3, mj = lane & 7;
    auto F = [](uint32_t x) { return __uint_as_float(x); };
    uint32_t KH[NC][2][8];
    TS(2);
    fft_forward<NC, false>(a1, tw, eo, s23, KH, [] {});
    named_bar(1 + wg, 128);
    uint4 a4[4];
#pragma unroll
    for (int i = 0; i < 4; i++) if (NC == 2) { tw[i] = ldg_tab(4 + i, t); a4[i] = ldg_tab(12 + i, t); }
    wg_wait<0>();
    TS(4);
    idle();
    uint2 x[NC][2][2];
    const uint32_t ra[2] = {4u * t, 4u * (t ^ 252)};
    auto stats = [&] {
        uint4 s[8];
        TS(1);
#pragma unroll
        for (int i = 0; i < 8; i++) s[i] = make_uint4(layer, 0, 0, 0);
        int spin = 0;
        uint32_t bad;
        do {
            bad = 0;
#pragma unroll
            for (int i = 0; i < 8; i++)
                if (miss(0, s[i].x, layer ^ 1) & 1u) s[i] = ld_ll4((const uint4*)(g_fs[0] + ra[i >> 2] + (SEQ * (i & 1) + 1024 * ((i >> 1) & 1))));
#pragma unroll
            for (int i = 0; i < 8; i++) bad = miss(bad, s[i].x, layer ^ 1);
        } while ((bad & 1u) && ++spin < (1 << 18));
#pragma unroll
        for (int i = 0; i < 8; i++) sts128(st + i * 2048 + t * 16, s[i]);
        __syncwarp();
        if (lane == 0) mbar_arrive(sbar + 8 * w);
        TS(14);
    };
    {
        const int tile = ((2 * w + (lane & 1)) ^ ((lane & 2) ? 15 : 0)) + 4 * (lane & 4);
        const bf16* pp = g_x1T + (uint32_t)(ch0 + NC - 1) * XP + 64 * tile + 60;
        uint32_t v;
        int spin = 0;
        do { asm volatile("ld.relaxed.gpu.global.u32 %0, [%1];" : "=r"(v) : "l"(pp) : "memory"); } while (__any_sync(~0u, ~(v ^ layer) & 1u) && ++spin < HINT_SPINS);
    }
    TS(5);
    auto xload = [&](int i) {
        const unsigned long long v = ld_ll((const unsigned long long*)(g_x1T + (uint32_t)ch0 * XP + ra[(i >> 1) & 1] + ((i >> 2) * XP + 1024 * (i & 1))));
        x[i >> 2][(i >> 1) & 1][i & 1] = make_uint2((uint32_t)v, (uint32_t)(v >> 32));
    };
#pragma unroll
    for (int i = 0; i < 4 * NC; i++) xload(i);
    TS(6);
    if (NC == 1) stats();
    for (int spin = 0; spin < (1 << 18); spin++) {
        uint32_t bad = 0;
#pragma unroll
        for (int i = 0; i < 4 * NC; i++) bad = miss(bad, x[i >> 2][(i >> 1) & 1][i & 1].x, layer ^ 1);
        if (!(bad & 1u)) break;
#pragma unroll
        for (int i = 0; i < 4 * NC; i++) if (miss(0, x[i >> 2][(i >> 1) & 1][i & 1].x, layer ^ 1) & 1u) xload(i);
    }
    __syncwarp();
#pragma unroll
    for (int i = 0; i < 4; i++) if (NC == 1) { tw[i] = ldg_tab(4 + i, t); a4[i] = ldg_tab(12 + i, t); }
    TS(26);
    if (NC == 2) mbar_wait(sbar + 8 * w, 0);
    staged();
    {
        uint4 s[2][2][2];
        uint32_t u[NC][2][4];
#pragma unroll
        for (int h = 0; h < 2; h++) {
            if (NC == 1 || h == 0) {
#pragma unroll
                for (int i = 4 * h; i < (NC == 1 ? 4 * h + 4 : 8); i++) s[i >> 2][(i >> 1) & 1][i & 1] = lds128(st + i * 2048 + t * 16);
            }
            if (h == 0) TS(7);
#pragma unroll
            for (int c = 0; c < NC; c++)
#pragma unroll
                for (int j = 0; j < 4; j++) {
                    const uint4 &a = s[h][j >> 1][0], &b = s[h][j >> 1][1];
                    const uint32_t xv = (j & 1) ? x[c][h][j >> 1].y : x[c][h][j >> 1].x;
                    u[c][h][j] = pack2h(fmaf(bf_lo(xv), F(u4(a, 2 * (j & 1))), F(u4(b, 2 * (j & 1)))), fmaf(bf_hi(xv), F(u4(a, 2 * (j & 1) + 1)), F(u4(b, 2 * (j & 1) + 1))));
                }
        }
#pragma unroll
        for (int c = 0; c < NC; c++) fft_stage<NC>(u[c], c, eo, w, lane);
    }
    TS(8);
    fence_async_smem();
    TS(9);
    named_bar(1 + wg, 128);
    uint32_t X[NC][2][8], Y[NC][2][8];
    uint32_t oscale[NC];
    fft_forward<NC, true>(a1, tw, eo, s23, X, [&] {
#pragma unroll
        for (int c = 0; c < NC; c++) oscale[c] = (lds32(kexp + 4 * c) + 3u) * 0x00800080u;
        if (layer) {
#pragma unroll
            for (int i = 0; i < 4 * NC; i++) asm volatile("mov.b32 %0, 0;\nmov.b32 %1, 0;" : "=r"(x[i >> 2][(i >> 1) & 1][i & 1].x), "=r"(x[i >> 2][(i >> 1) & 1][i & 1].y));
        }
        if (NC == 2 && wg == 1 && lane == 0) mbar_arrive(fbar);
        TS(3); if (F_STAG >= 2 && NC == 2 && wg == 1) named_bar(10 + w, 64); });
    if (F_STAG == 2 && NC == 2 && wg == 0) asm volatile("bar.arrive %0, 64;" ::"r"(10 + w) : "memory");
    TS(10);
    const uint64_t d3 = mkdesc(s23 + 4096, 16, 1024, 1);
#pragma unroll
    for (int c = 0; c < NC; c++) {
        wg_wait<NC - 1>();
        TS(11 + c);
        uint4 pr[2], pi[2];
#pragma unroll
        for (int i = 0; i < 4; i++) {
            const uint32_t er = X[c][0][i], ei = X[c][0][4 + i], orr = X[c][1][i], oi = X[c][1][4 + i];
            const uint32_t ar = KH[c][0][i], ai = KH[c][0][4 + i], br = KH[c][1][i], bi = KH[c][1][4 + i];
            u4r(pr[0], i) = hfms(bi, oi, hfma(br, orr, hfms(ai, ei, hmul(ar, er))));
            u4r(pi[0], i) = hfma(bi, orr, hfma(br, oi, hfma(ai, er, hmul(ar, ei))));
            u4r(pr[1], i) = hfms(ai, oi, hfma(ar, orr, hfms(bi, ei, hmul(br, er))));
            u4r(pi[1], i) = hfma(ai, orr, hfma(ar, oi, hfma(bi, er, hmul(br, ei))));
        }
        if (F_STAG == 3 + c && NC == 2 && wg == 0) asm volatile("bar.arrive %0, 64;" ::"r"(10 + w), "r"(pr[0].x ^ pr[1].w ^ pi[0].y ^ pi[1].z) : "memory");
        wg_fence();
        wgmma_h32_rs<0>(Y[c][0], pr[0], d3, 0);
        wgmma_h32_rs<0>(Y[c][1], pr[1], d3 + 4, 0);
        wgmma_h32_rs<0>(Y[c][0], pi[0], d3 + 2, 1);
        wgmma_h32_rs<0>(Y[c][1], pi[1], d3 + 6, 1);
        wg_commit();
    }
#pragma unroll
    for (int c = 0; c < NC; c++) {
        if (c + 1 < NC) wg_wait<1>(); else wg_wait<0>();
        TS(13 + c);
        uint32_t zr[2][4], zi[2][4];
#pragma unroll
        for (int p = 0; p < 2; p++)
#pragma unroll
            for (int i = 0; i < 4; i++) {
                const uint32_t r = Y[c][p][i], m = Y[c][p][4 + i], tr = u4(tw[p], i), ti = u4(tw[2 + p], i);
                const uint32_t r1 = hfms(tr, m, r), m1 = hfms(ti, r1, m);
                zr[i & 1][2 * p + (i >> 1)] = hfms(tr, m1, r1);
                zi[i & 1][2 * p + (i >> 1)] = m1;
            }
        const int kr = 4 * (mj >> 1) + (mj & 1) + 2 * (mj >> 2), ki = kr ^ 2;
#pragma unroll
        for (int h = 0; h < 2; h++) {
            const uint32_t a = zb + (2 * w + h) * 2048;
            stsm_x4(a + ki * 128 + (((4 * c + mi) ^ (ki & 7)) << 4), zi[h][0], zi[h][1], zi[h][2], zi[h][3]);
            stsm_x4(a + kr * 128 + (((4 * c + mi) ^ (kr & 7)) << 4), zr[h][0], zr[h][1], zr[h][2], zr[h][3]);
        }
    }
    TS(15);
    fence_async_smem();
    TS(16);
    named_bar(1 + wg, 128);
    TS(17);
    float acc[16 * NC];
    const uint64_t dz = mkdesc(zb, 4096, 1024, 1);
    wg_fence();
#pragma unroll
    for (int ks = 0; ks < 4; ks++) wgmma_s4(acc, a4[ks], dz + ks * 256, 0x44EEEE44u, ks > 0);
    wg_commit();
    const uint32_t fb = ~lds32(epoch);
    uint32_t mk[NC][2][4];
    const char* dst[2];
    {
        uint32_t l2;
        asm volatile("mov.u32 %0, %%laneid;" : "=r"(l2));
        const char* base = layer ? (const char*)g_of + (uint32_t)(ch0 / 80) * 327680u + (uint32_t)(ch0 % 80) * 256u : (const char*)g_x2T + (uint32_t)ch0 * (XP * 2u);
        const uint32_t k0 = layer ? 8 : (ch0 >> 1) & 3;
        uint32_t m0[2] = {k0 == 2 * (l2 & 3), k0 == 2 * (l2 & 3) + 1}, m1[2][2];
#pragma unroll
        for (int h = 0; h < 2; h++) {
            const uint32_t v = (32 * w + l2) ^ (h ? 252u : 0u);
            dst[h] = base + (layer ? (v >> 4) * 20480u + (v & 15u) * 16u : v * 8u);
            m1[h][0] = m0[0] | (~(v >> 3) & layer); m1[h][1] = m0[1] | ((v >> 3) & layer);
            asm volatile("" : "+l"(dst[h]), "+r"(m1[h][0]), "+r"(m1[h][1]), "+r"(m0[h]), "+r"(oscale[h % NC]));
        }
#pragma unroll
        for (int i = 0; i < 8 * NC; i++) {
            const int c = i >> 3, h = (i >> 2) & 1, j = i & 3;
            mk[c][h][j] = (j >> 1) == (NC == 2 ? c : ch0 & 1) ? m1[h][j & 1] : m0[j & 1];
            if (NC == 1) asm volatile("" : "+r"(mk[c][h][j]));
        }
        mbar_wait(sbar, 0);
    }
    auto mark = [&](uint32_t v, uint32_t m) { return (v & ~m) | (fb & m); };
    wg_wait<0>();
    TS(18);
#pragma unroll
    for (int c = 0; c < NC; c++) {
        uint32_t r[2][4];
#pragma unroll
        for (int j = 0; j < 4; j++) {
            const float* d = acc + 4 * (4 * c + j);
            const uint32_t y0 = pack2(d[0] + d[2], d[1] + d[3]), y1 = pack2(d[0] - d[2], d[1] - d[3]);
            asm("fma.rn.bf16x2 %0, %1, %2, %3;" : "=r"(r[0][j]) : "r"(y0), "r"(oscale[c]), "r"((j & 1) ? x[c][0][j >> 1].y : x[c][0][j >> 1].x));
            asm("fma.rn.bf16x2 %0, %1, %2, %3;" : "=r"(r[1][j]) : "r"(y1), "r"(oscale[c]), "r"((j & 1) ? x[c][1][j >> 1].y : x[c][1][j >> 1].x));
        }
#pragma unroll
        for (int h = 0; h < 2; h++)
            asm volatile("{\n.reg .pred p;\n.reg .b128 t;\n.reg .b64 a, b;\nsetp.ne.u32 p, %5, 0;\nmov.b64 a, {%1, %2};\nmov.b64 b, {%3, %4};\nmov.b128 t, {a, b};\n"
                         "@p st.relaxed.gpu.global.b128 [%0], t;\n@!p st.relaxed.gpu.global.b64 [%6], a;\n@!p st.relaxed.gpu.global.b64 [%6 + 2048], b;\n}"
                         ::"l"(dst[h] + c * 256), "r"(mark(r[h][0], mk[c][h][0])), "r"(mark(r[h][1], mk[c][h][1])), "r"(mark(r[h][2], mk[c][h][2])), "r"(mark(r[h][3], mk[c][h][3])), "r"(layer), "l"(dst[h] + c * XP * 2) : "memory");
    }
    if (layer == 0 && lane == 0) asm volatile("red.relaxed.gpu.global.add.u32 [%0], %1;" ::"l"(g_xcnt[ch0 >> 6][w]), "n"(NC) : "memory");
    TS(19);
}

#define Q_S0 8
#define R_CONS 192
#define K_CSUN 1
constexpr int K_CSU = K_CSUN;
#define G_MAP 1
constexpr int Q_SP = 4;
#define A_VLO 4
constexpr int Q_ST = 4;
constexpr int Q_AB = 16384, Q_BB = 30720, Q_SB = Q_AB + Q_BB;
constexpr int Q_EROW = 336;
constexpr int Q_ESLOT = 8 * Q_EROW;
constexpr int Q_EOFF = Q_ST * Q_SB;
constexpr int Q_KG = 2 * Q_SB;
static_assert(3 * Q_ESLOT <= 8192 && Q_KG + KG_TABLES <= Q_EOFF + 4096, "exchange slots, kernel generation");
constexpr int F_EO = Q_EOFF, F_S23 = F_EO + 2 * 8192 + 4096, Q_KDUMP = F_S23 + 8192;
constexpr int Q_MISC = Q_KDUMP + 6 * KG_RES;
__host__ __device__ constexpr int w_grp(int j) { return j ? 2 * Q_SB + 4096 + (j - 1) * 12800 : 0; }
constexpr int W_RES = Q_AB;
__device__ __forceinline__ int o_slot(int wg, int j) { return W_RES + wg * 10240 + (j & 3) * 20480; }
__device__ __forceinline__ int w_out(int wg) { return W_RES + (2 + 3 * wg) * 10240; }
static_assert(W_RES + 8 * 10240 == w_grp(1) && w_grp(7) + 12800 <= Q_EOFF && w_grp(4) <= 3 * Q_SB, "phase W layout");

constexpr int Q_WOT = Q_EOFF + 4096;

__device__ unsigned g_epoch;
__device__ __align__(1024) unsigned g_bar[4][16][32];
__device__ __align__(1024) uint4 g_wop[8][80][10][8];
__device__ __align__(1024) uint4 g_csp[8][16][96];
__device__ __align__(1024) uint4 g_stp[16][8][64];
__device__ __align__(1024) uint4 g_sp2[16][8][8][8];
__device__ __align__(1024) uint4 g_halo[128][2][5][32];

struct Bars { uint64_t full[Q_ST], empty[Q_ST], wfull, ex[7], res, go, qdone, prep, hdone, idx, fdone0, att[2], wfree, soon[2], fdone1, st[4], kfree, staged, xland[4], spec; };
constexpr int NBAR = sizeof(Bars) / 8;
struct OBars { uint64_t b[2][12]; };
struct Misc { float cs[240], mean[2][64], rstd[2][72]; Bars bar[2]; OBars ob; KgShared kg; uint32_t epoch, pad; };
#define MISC(f) (sb + Q_MISC + (uint32_t)offsetof(Misc, f))
constexpr int Q_SMEM = Q_MISC + sizeof(Misc) + TS_SMEM;
__host__ __device__ constexpr int bar_count(int i) {
#define BAR_IS(f) (i == offsetof(Bars, f) / 8)
    return (i >= 4 && i < 8) ? 16 : (BAR_IS(go) || (i >= offsetof(Bars, att) / 8 && i < offsetof(Bars, st) / 8)) ? 4 : (BAR_IS(qdone) || BAR_IS(fdone0)) ? 8 : BAR_IS(prep) ? 96 :
           BAR_IS(hdone) ? 6 : BAR_IS(kfree) ? 24 : BAR_IS(staged) ? 2 : 1;
}
__device__ __forceinline__ void grid_wait(const unsigned* c, int n, unsigned target, int lane) {
    const unsigned* p = c + 32 * min(lane, n - 1);
    unsigned v;
    int spin = 0;
    do { asm volatile("ld.relaxed.gpu.global.u32 %0, [%1];" : "=r"(v) : "l"(p) : "memory"); } while (!__all_sync(~0u, (int)(v - target) >= 0) && ++spin < (1 << 18));
    fence_acquire();
}
__device__ __forceinline__ void grid_arrive(unsigned* c) {
    fence_release();
    asm volatile("red.relaxed.gpu.global.add.u32 [%0], 1;" ::"l"(c) : "memory");
}

#define TMAP(n) ([] { const CUtensorMap* p_; asm volatile("{\n.reg .b64 t;\nmov.b64 t, fused_kernel_param_" #n ";\ncvta.param.u64 %0, t;\n}" : "=l"(p_)); return p_; }())
extern "C" __global__ void __launch_bounds__(384, 1)
fused_kernel(const SsmParams sp, const __grid_constant__ CUtensorMap mX0, const __grid_constant__ CUtensorMap mX1, const __grid_constant__ CUtensorMap mW,
             const __grid_constant__ CUtensorMap mWr,
             const __grid_constant__ CUtensorMap mRes0, const __grid_constant__ CUtensorMap mRes1, const __grid_constant__ CUtensorMap mOut,
             const __grid_constant__ CUtensorMap mWo, const __grid_constant__ CUtensorMap mFin, const __grid_constant__ CUtensorMap mResA) {
    extern __shared__ __align__(1024) char smraw[];
    const uint32_t sb = s2u(smraw);
    int tid, warp, lane, bx, rank, blk, hg, rot, c0;
    int role;
    {
        const int c = blockIdx.x >> 1, d = c - 41, r = d >= 21 ? 3 : d >= 14 ? 2 : d >= 7 ? 1 : 0;
        const int gp = c < 4 ? 0 : c <= 40 ? (c + 7) & 7 : d - 7 * r + 1;
        const int k = c < 4 ? c : c <= 40 ? (c >> 3) + (gp == 0 ? 3 : gp >= 3 && gp < 7 ? 0 : -1) : (gp >= 3 ? 5 : 4) + r;
        role = G_MAP == 1 ? 16 * k + 2 * gp + (blockIdx.x & 1) : G_MAP == 2 ? 16 * gp + 2 * k + (blockIdx.x & 1) : blockIdx.x;
    }
    auto indices = [&] {
        asm volatile("mov.u32 %0, %%tid.x;" : "=r"(tid));
        asm volatile("mov.u32 %0, %1;" : "=r"(bx) : "r"(role));
        warp = __shfl_sync(~0u, tid >> 5, 0); lane = tid & 31;
        rank = bx & 1; blk = bx & 15; hg = bx >> 4;
        const int u = ((blk >> 1) + hg) & 7;
        rot = (5 * u) >> 2; c0 = 16 * (u & 3);
    };
    indices();
    TS_DECL;
    TS_BEGIN;
#define EPOCH lds32(MISC(epoch))
    int layer = 0;
    uint32_t bars = MISC(bar);
#define BAR(f) (bars + (uint32_t)offsetof(Bars, f))
    auto chunk = [&](int it, int s0) {
        const int i = it < s0 ? it : it - 2;
        return (it >> 1) == (s0 >> 1) ? rot + (it & 1) : i < rot ? i : i + 2;
    };
    auto osrc_of = [&](int j) { return j == 0 ? hg : j - 1 < hg ? j - 1 : j; };
    auto issue_w = [&](uint32_t bb, int it, int lay) {
        const int half = rank;
        const int s = it & (Q_ST - 1);
        const uint32_t fb = bb + 8 * s, db = sb + s * Q_SB + Q_AB + half * 15360;
        const int k0 = chunk(it, Q_SP * lay) * 64 + half * 32;
#pragma unroll
        for (int p = 0; p < 3; p++) tma2d_mc(db + p * 4096, TMAP(3), p * DM + hg * 80, k0, fb, 3);
        tma3d_mc(db + 12288, TMAP(4), hg * 80 + 64, k0, 0, fb, 3);
    };
    auto issue_x = [&](int it) {
        const int s = it & (Q_ST - 1), kc = chunk(it, Q_SP * layer);
        mbar_expect(BAR(full) + 8 * s, Q_SB);
        tma3d(sb + s * Q_SB, TMAP(1) + layer, (layer ? blk : kc) * 64, (layer ? kc : blk) * 64, 0, BAR(full) + 8 * s);
    };
    {
        KgParams kp;
        const uint32_t epoch0 = ldg32(sp.epoch);
        kgen_load(kp, bx, warp, lane, sp);
        if (warp < 8) {
            cluster_arrive_relaxed();
        } else {
            if (elect_one()) {
                if (warp < 10) { prefetch_tmap(TMAP(3)); prefetch_tmap(TMAP(4)); } else prefetch_tmap(warp == 10 ? TMAP(1) : TMAP(8));
                const uint32_t b0 = bars + (warp >= 10 ? sizeof(Bars) : 0);
                if (warp & 1) {
#pragma unroll
                    for (int i = 0; i < NBAR / 2; i++) mbar_init(b0 + i * 8, bar_count(i));
                } else {
#pragma unroll
                    for (int i = NBAR / 2; i < NBAR; i++) mbar_init(b0 + i * 8, bar_count(i));
                }
                fence_mbar_init();
            }
            __syncwarp();
            cluster_arrive_relaxed();
            TS(29);
            cluster_wait();
            TS(27);
            if (elect_one()) {
                if (warp < 10) {
                    issue_w(BAR(full), warp - 8, 0);
                } else if (warp == 10) {
                    issue_x(0); issue_x(1);
                    prefetch_l2((const char*)c_fft + bx * (sizeof(c_fft) / 128), sizeof(c_fft) / 128);
                } else {
                    mbar_expect(BAR(idx), 8192 + 6400);
                    asm volatile("cp.async.bulk.tensor.4d.shared::cluster.global.mbarrier::complete_tx::bytes [%0], [%1, {0, 0, %3, %4}], [%2];"
                                 ::"r"(sb + Q_WOT), "l"(TMAP(8)), "r"(BAR(idx)), "r"(10 * hg), "r"(5 * blk) : "memory");
                    bulk_g2s(sb + F_S23, c_fft + 18 * 512, 8192, BAR(idx));
                }
            }
            __syncwarp();
            TS(30);
        }
        indices();
        kgen_tables(kp, sb + Q_KG, sb + Q_KDUMP, MISC(kg), warp, lane, [&] { if (warp < 8) cluster_wait(); } TS_PASS);
        __syncwarp();
        if (lane == 0) { mbar_arrive_cta(BAR(kfree), 0); mbar_arrive_cta(BAR(kfree), 1); }
        if (warp >= 8) {
            const int t2 = tid - 256;
            float csum[10];
            if (warp < 10 && elect_one()) {
#pragma unroll
                for (int i = 1; i < 12; i++) mbar_init(MISC(ob) + (warp - 8) * 96 + i * 8, i < 8 ? 1 : 4);
                fence_mbar_init();
            }
            __syncwarp();
            if (t2 == 0) sts32(MISC(epoch), epoch0);
            if (t2 < 64) stg128(&g_sp2[blk][hg][0][0] + t2, make_uint4(0, 0, 0, 0));
            if (t2 >= 64 && t2 < 80) stg128(&g_of[hg][blk][640 * ((t2 >> 3) & 1) + 8 * (73 + (t2 & 6)) + 6 + (t2 & 1)], make_uint4(epoch0, epoch0, epoch0, epoch0));
            if (t2 >= 120) stg128((uint4*)g_fs + 8 * bx + t2 - 120, make_uint4(0, 0, 0, 0));
#pragma unroll
            for (int i = 0; i < 2; i++)
                if (t2 + 128 * i < 192) stg128(g_x1T + (uint32_t)cta_channel(bx, 4 * i + 1 + 2 * (t2 >> 6)) * XP + 32 * (t2 & 62) + 48 + 8 * (t2 & 1), make_uint4(0, 0, 0, 0));
#pragma unroll
            for (int i = 0; i < 3; i++)
                if (t2 + 128 * i < 320) stg128(&g_halo[bx][0][0][0] + t2 + 128 * i, make_uint4(0, 0, 0, 0));
            named_bar(13, 128);
            if (warp > 8) {
                const int hw = warp - 9, mi = lane >> 3, mj = lane & 7;
                mbar_wait(BAR(idx), 0);
                if (hw == 2 && elect_one()) { bulk_s2g(&g_wop[hg][5 * blk], sb + Q_WOT, 6400); bulk_commit(); }
                __syncwarp();
                mbar_wait(BAR(full), 0);
                mbar_wait(BAR(full) + 8, 0);
#pragma unroll
                for (int f = 0; f < 10; f++) csum[f] = 0.f;
#pragma unroll K_CSU
                for (int G = 0; G < 5; G++) {
                    const int row = c0 + 40 * rank + 8 * G + mj;
                    const uint32_t b = sb + (row >> 6) * Q_SB + Q_AB + ((row >> 5) & 1) * 15360;
                    uint32_t r[10];
                    ldsm_x4_t(r[0], r[1], r[2], r[3], b + hw * 4096 + (row & 31) * 128 + ((mi ^ mj) << 4));
                    ldsm_x4_t(r[4], r[5], r[6], r[7], b + hw * 4096 + (row & 31) * 128 + (((4 + mi) ^ mj) << 4));
                    ldsm_x2_t(r[8], r[9], b + 12288 + hw * 1024 + (row & 31) * 32 + (((mi & 1) ^ (mj >> 2)) << 4));
#pragma unroll
                    for (int f = 0; f < 10; f++) csum[f] += bf_lo(r[f]) + bf_hi(r[f]);
                }
                const int q = lane & 3;
                float t[3];
#pragma unroll
                for (int j = 0; j < 3; j++) {
                    float v[4];
#pragma unroll
                    for (int k = 0; k < 4; k++) v[k] = 4 * j + k < 10 ? csum[4 * j + k] : 0.f;
                    const float a0 = ((q & 2) ? v[2] : v[0]) + __shfl_xor_sync(~0u, (q & 2) ? v[0] : v[2], 2);
                    const float a1 = ((q & 2) ? v[3] : v[1]) + __shfl_xor_sync(~0u, (q & 2) ? v[1] : v[3], 2);
                    t[j] = ((q & 1) ? a1 : a0) + __shfl_xor_sync(~0u, (q & 1) ? a0 : a1, 1);
                }
                st_ll4(&g_csp[hg][blk][tid - 288], ~EPOCH & 1u, __float_as_uint(t[0]), __float_as_uint(t[1]), __float_as_uint(t[2]));
            }
        }
        TS(1);
    }

    uint4 fa1[4], ftw[4];
    auto conv_tables = [&] {
#pragma unroll
        for (int i = 0; i < 4; i++) { fa1[i] = ldg_tab(i, tid & 127); ftw[i] = ldg_tab(8 + i, tid & 127); }
    };
    if (warp >= 8) {
    asm volatile("setmaxnreg.dec.sync.aligned.u32 %0;" ::"n"(504 - 2 * R_CONS));
#pragma unroll 1
    for (; layer < 2; layer++, bars += sizeof(Bars)) {
        indices();
        TS_PHASE(2 * layer);
        if (layer) {
            const int i = warp - 8, g = lane >> 2;
            const uint32_t eb = ~EPOCH, a = sb + i * Q_SB + g * 128 + (((2 * (lane & 3)) ^ g) << 4) + 2 * (g & 6);
            const unsigned* pp = g_xcnt[chunk(i, Q_SP)][(blk < 8 ? blk : 15 - blk) >> 1];
            mbar_wait(BAR(fdone0) - sizeof(Bars), 0);
            if (i == 3) mbar_wait(BAR(fdone1) - sizeof(Bars), 0);
            if (i == 3 && elect_one()) grid_arrive(g_bar[2][hg]);
            __syncwarp();
            uint32_t bad;
            int spin = 0;
            do { asm volatile("ld.relaxed.gpu.global.u32 %0, [%1];" : "=r"(bad) : "l"(pp) : "memory"); } while ((int)(bad + 64 * eb) < 0 && ++spin < HINT_SPINS);
            fence_async_global();
            TS(1);
            spin = 0;
            do {
                if (elect_one()) {
                    mbar_expect(BAR(xland) + 8 * i, Q_AB);
                    tma3d(sb + i * Q_SB, TMAP(2), blk * 64, chunk(i, Q_SP) * 64, 0, BAR(xland) + 8 * i);
                }
                __syncwarp();
                mbar_wait(BAR(xland) + 8 * i, spin & 1);
                bad = 0;
#pragma unroll
                for (int k = 0; k < 16; k++) bad = miss(bad, lds32(a + k * 1024), eb);
            } while (__any_sync(~0u, bad & 1u) && ++spin < (1 << 16));
            if (lane == 0) mbar_expect(BAR(full) + 8 * i, Q_BB);
            TS(9);
        }
        if (warp == 8) {
            if (layer) {
                grid_wait(g_bar[2][0], 8, 16 * (EPOCH + 1), lane);
                fence_async_global();
                TS(10);
            }
            if (elect_one()) {
#pragma unroll 1
                for (int it = 2 + 2 * layer; it < 10; it++) {
                    if (it >= Q_ST) mbar_wait(BAR(empty) + 8 * (it & (Q_ST - 1)), ((it >> 2) - 1) & 1);
                    else mbar_wait(BAR(kfree), 0);
                    if (it == Q_ST + Q_SP * layer) mbar_wait(BAR(hdone), 0);
                    issue_x(it);
                    issue_w(BAR(full), it, layer);
                    if (it == Q_SP + 1) mbar_arrive(BAR(spec));
                }
                { prefetch_tmap(TMAP(5) + layer); prefetch_tmap(TMAP(7)); prefetch_tmap(TMAP(10)); }
                if (layer == 0) { mbar_wait(BAR(prep), 0); fence_async_global(); }
#pragma unroll 1
                for (int n = 1; n < 9; n++) {
                    const int b = n >> 2, j = n & 7;
                    if (n == 1 || !(n & 3)) { mbar_wait(BAR(empty) + 8 * ((2 + b) & 3), b < 2); TS(11 + b); }
                    bulk_g2s_mc(sb + w_grp(j) + rank * 6400, &g_wop[hg][osrc_of(j) * 10 + rank * 5], 6400, BAR(wfull), 3);
                }
                mbar_expect(BAR(wfull), 8 * 12800);
                mbar_expect(BAR(res), 20480);
                if (layer) {
                    tma3d(sb + W_RES, TMAP(6), blk * 64, hg * 80, 0, BAR(res));
                } else {
#pragma unroll 1
                    for (int p = 0; p < 2; p++) {
                        tma3d(sb + W_RES + p * 10240, TMAP(10), hg * 80, blk * 64, p, BAR(res));
                        tma3d(sb + W_RES + p * 10240 + 8192, TMAP(5), hg * 80 + 64, blk * 64, p, BAR(res));
                    }
                }
            }
            __syncwarp();
        } else {
            const int ht = tid - 288, hw = warp - 9, mi = lane >> 3, mj = lane & 7, g = lane >> 2, q = lane & 3;
            auto F = [](uint32_t x) { return __uint_as_float(x); };
            auto U = [](float x) { return __float_as_uint(x); };
            const uint32_t lb = layer ^ 1, eb = ~EPOCH & 1u;
            if (layer) mbar_wait(BAR(spec), 0);
            mbar_wait(BAR(full), layer);
            mbar_wait(BAR(full) + 8, layer);
            if (ht == 0) TSX(2, 2);
            uint32_t xf[3][20];
#pragma unroll
            for (int i = 0; i < 3; i++) {
                const int tile = min(hw + 3 * i, 7);
#pragma unroll
                for (int k = 0; k < 5; k++) {
                    const int ch = c0 + 16 * k + 8 * (mi >> 1), tok = 16 * (tile & 3) + 8 * (mi & 1);
                    const uint32_t a = sb + (ch >> 6) * Q_SB + (tile >> 2) * 8192;
                    if (layer == 0) ldsm_x4(xf[i][4 * k], xf[i][4 * k + 1], xf[i][4 * k + 2], xf[i][4 * k + 3], a + (tok + mj) * 128 + ((((ch & 63) >> 3) ^ mj) << 4));
                    else ldsm_x4_t(xf[i][4 * k], xf[i][4 * k + 1], xf[i][4 * k + 2], xf[i][4 * k + 3], a + ((ch & 63) + mj) * 128 + (((tok >> 3) ^ mj) << 4));
                }
            }
            fence_async_smem();
            __syncwarp();
            if (lane == 0) { mbar_arrive_cta(BAR(hdone), 0); mbar_arrive_cta(BAR(hdone), 1); }
            if (ht == 0) TSX(2, 3);
            if (layer == 0) {
                if (hw == 2 && elect_one()) { bulk_wait(); fence_async_global(); grid_arrive(g_bar[3][hg]); }
                __syncwarp();
                mbar_wait(BAR(kfree), 0);
            }
            if (ht == 0) TSX(2, 8);
#pragma unroll 1
            for (int tile = hw; tile < 8; tile += 3) {
                float a[4] = {0.f, 0.f, 0.f, 0.f};
#pragma unroll
                for (int j = 0; j < 20; j++) {
                    const float lo = bf_lo(xf[0][j]), hi = bf_hi(xf[0][j]);
                    a[2 * (j & 1)] += lo + hi; a[2 * (j & 1) + 1] = fmaf(lo, lo, fmaf(hi, hi, a[2 * (j & 1) + 1]));
                    xf[0][j] = xf[1][j]; xf[1][j] = xf[2][j];
                }
#pragma unroll
                for (int j = 0; j < 4; j++) { a[j] += __shfl_xor_sync(~0u, a[j], 1); a[j] += __shfl_xor_sync(~0u, a[j], 2); }
                if (q == 0) st_ll4(&g_stp[blk][hg][8 * tile + g], (U(a[0]) & ~1u) | lb, U(a[1]), U(a[2]), U(a[3]));
            }
            if (ht == 0) TSX(2, 4);
            if (layer == 0) {
                float t[4] = {0.f, 0.f, 0.f, 0.f};
                uint4 v[16];
                int spin = 0;
                uint32_t bad;
                do {
                    bad = 0;
#pragma unroll
                    for (int j = 0; j < 16; j++) v[j] = ld_ll4(&g_csp[hg][j][ht]);
#pragma unroll
                    for (int j = 0; j < 16; j++) bad = miss(bad, v[j].x, eb);
                } while ((bad & 1u) && ++spin < (1 << 18));
#pragma unroll
                for (int j = 0; j < 16; j++) { t[0] += F(v[j].y); t[1] += F(v[j].z); t[2] += F(v[j].w); }
#pragma unroll
                for (int j = 0; j < 3; j++) if (q + 4 * j < 10) sts32(MISC(cs) + 4 * (80 * hw + 20 * (g >> 1) + 2 * (q + 4 * j) + (g & 1)), U(t[j]));
                if (hw == 2) grid_wait(g_bar[3][0], 8, 16 * (EPOCH + 1), lane);
            }
            if (ht == 0) TSX(2, 15);
            if (ht < 80) {
                const bool halo = ht >= 64;
                const int p = halo ? (ht >> 3) & 1 : ht >> 5, i = halo ? (ht & 7) - 8 : 8 + 2 * (ht & 24) + (ht & 7);
                const uint4* src = &g_stp[halo && blk ? blk - 1 : blk][0][halo ? 32 * p + 24 + (ht & 7) : ht];
                uint4 v[8];
                int spin = 0;
                uint32_t bad;
                do {
                    bad = 0;
#pragma unroll
                    for (int j = 0; j < 8; j++) v[j] = ld_ll4(src + 64 * j);
#pragma unroll
                    for (int j = 0; j < 8; j++) bad = miss(bad, v[j].x, lb);
                } while ((bad & 1u) && ++spin < (1 << 18));
                float t[4] = {0.f, 0.f, 0.f, 0.f};
#pragma unroll
                for (int j = 0; j < 8; j++) { t[0] += F(v[j].x); t[1] += F(v[j].y); t[2] += F(v[j].z); t[3] += F(v[j].w); }
                const uint32_t s0 = ln_finish_packed(t[0], t[1]), s1 = ln_finish_packed(t[2], t[3]);
                const uint32_t am = MISC(mean) + 4 * (64 * p + i), ar = MISC(rstd) + 4 * (72 * p + i);
                if (!halo) { sts32(am - 32, U(bf_hi(s0))); sts32(am, U(bf_hi(s1))); sts32(ar, U(frcp(bf_lo(s0)))); }
                sts32(ar + 32, U(frcp(bf_lo(s1))));
            }
            fence_acquire();
            mbar_arrive(BAR(prep));
            if (ht == 0) TSX(2, 5);
        }
        __syncwarp();
        indices();
        {
            const uint4 ko[2] = {ldg_tab(16, tid & 127), ldg_tab(17, tid & 127)};
            conv_tables();
            kernel_stage<1>(ko, sb + Q_KDUMP + 4 * KG_RES, MISC(kg), 4, sb + F_EO + 2 * 8192, warp & 3, lane);
            fence_async_smem();
        }
        {
            const int p = warp & 1;
            const uint32_t fb = EPOCH ^ layer ^ 1, ob = MISC(ob) + 96 * p;
            if (warp >= 10) {
                const uint32_t* pp = &g_of[osrc_of(1 + min(lane >> 2, 6))][blk][640 * p + 8 * (73 + 2 * (lane & 3)) + 7].x + 1 + 2 * (lane & 1);
                mbar_wait(BAR(qdone), 0);
                mbar_wait(BAR(att) + 8 * p, 0);
                const char* src = (const char*)&g_of[0][blk][640 * p];
                uint32_t late = ~0u, need = 15u, bar = ob + 8;
                int spin = 0;
#pragma unroll 1
                for (int j = 1; j < 8; j++, need <<= 4, bar += 8, src += 327680) {
                    while ((late & need) && ++spin < HINT_SPINS) {
                        uint32_t v;
                        asm volatile("ld.relaxed.gpu.global.u32 %0, [%1];" : "=r"(v) : "l"(pp) : "memory");
                        late = __ballot_sync(~0u, miss(0, v, fb) & 1u);
                        fence_async_global();
                    }
                    if (j == 1) TS(16);
                    if (j - 1 == hg) src += 327680;
                    if (j > 3) mbar_wait(bar + 32, layer);
                    if (elect_one()) { mbar_expect(bar, 10240); bulk_g2s(sb + o_slot(p, j), src, 10240, bar); }
                }
                __syncwarp();
                TS(17);
            }
        }
        TS_PHASE(2 * layer + 1);
        TS(0);
        indices();
        named_bar(3, 128);
        conv_wg<1>(cta_channel(bx, 4), layer, sb + F_EO + 2 * 8192, sb + 2 * Q_SB, sb + F_S23, MISC(kg.kexp) + 16, MISC(epoch), sb, BAR(st), 0,
                   warp, lane, fa1, ftw,
        [&] {
            if (warp == 9) {
                auto F = [](uint32_t x) { return __uint_as_float(x); };
                mbar_wait(BAR(soon) + 8 * (hg >> 2), 0);
                TS(23);
                const uint4* src = &g_sp2[blk][hg][0][0] + lane;
                uint4* dst = (uint4*)(g_fs[(lane >> 2) & 1] + 1024 * (hg >> 2) + 64 * blk + 16 * (hg & 3)) + (lane & 3);
                const bool up = lane & 8;
#pragma unroll 1
                for (int spin = 0; spin < (1 << 18); spin++) {
                    const uint4 a = ld_ll4(src), b = ld_ll4(src + 32);
                    const bool ok = !__any_sync(~0u, miss(miss(0, a.x, layer ^ 1), b.x, layer ^ 1) & 1u);
                    const float s0 = F(a.x) + F(b.x), q0 = F(a.y) + F(b.y), s1 = F(a.z) + F(b.z), q1 = F(a.w) + F(b.w);
                    float sm = (up ? s1 : s0) + __shfl_xor_sync(~0u, up ? s0 : s1, 8), sq = (up ? q1 : q0) + __shfl_xor_sync(~0u, up ? q0 : q1, 8);
                    sm += __shfl_xor_sync(~0u, sm, 16); sq += __shfl_xor_sync(~0u, sq, 16);
                    const float m = sm * (1.0f / DM), r = frsq(fmaxf(fmaf(sq, 1.0f / DM, fmaf(-m, m, 1e-5f)), 1e-5f));
                    const uint32_t v = __float_as_uint(lane & 16 ? -m * r : r);
                    const uint32_t v0 = __shfl_sync(~0u, v, 4 * lane), v1 = __shfl_sync(~0u, v, 4 * lane + 1), v2 = __shfl_sync(~0u, v, 4 * lane + 2), v3 = __shfl_sync(~0u, v, 4 * lane + 3);
                    if (ok && lane < 8) st_ll4(dst, (v0 & ~1u) | (layer ^ 1), v1, v2, v3);
                    if (ok) break;
                }
            }
            TS(25);
            mbar_wait(BAR(staged), 0);
        }, [&] {
            if (tid == 352) prefetch_tmap(layer ? TMAP(9) : TMAP(2));
        } TS_PASS);
        named_bar(3, 128);
        TS(20);
    }
    } else {
#pragma unroll 1
    for (; layer < 2; layer++, bars += sizeof(Bars)) {
    indices();
    TS_PHASE(2 * layer);
    const int wg = warp >> 2, w = warp & 3;
    const int mi = lane >> 3, mj = lane & 7, g = lane >> 2, q = lane & 3;
    TS(2);
    float acc[120];
#pragma unroll
    for (int i = 0; i < 120; i++) acc[i] = 0.f;
    auto release = [&](int it) {
        if (lane == 0) { mbar_arrive_cta(BAR(empty) + 8 * (it & (Q_ST - 1)), 0); mbar_arrive_cta(BAR(empty) + 8 * (it & (Q_ST - 1)), 1); }
    };
#pragma unroll 1
    for (int it = 0; it < 10; it++) {
        const int s = it & (Q_ST - 1);
        const uint32_t st = sb + s * Q_SB;
        const bool hold = wg == 1 && it == Q_S0;
        if (hold) {
            wg_wait<0>();
            release(it - 1);
            mbar_wait(BAR(go), 0);
        }
        mbar_wait(BAR(full) + 8 * (s), (it >> 2) & 1);
        if (it < 2) TS(3 + it);
        if (it == 6) TS(5);
        if (it == 9) TS(6);
        const uint64_t da = mkdesc(st + wg * 8192, 16, 1024, 1);
        const uint64_t db = mkdesc(st + Q_AB, 4096, 1024, 1);
        const uint64_t dr = mkdesc(st + Q_AB + 12288, 1024, 256, 3);
        if (layer == 0) {
            wg_fence();
#pragma unroll
            for (int ks = 0; ks < 4; ks++) {
                const int sc = 1;
                wgmma_n192<0, 1>(*(float(*)[96]) & acc[0], da + ks * 2, db + (ks >> 1) * 960 + (ks & 1) * 128, sc);
                wgmma_n48<0, 1>(*(float(*)[24]) & acc[96], da + ks * 2, dr + (ks >> 1) * 960 + (ks & 1) * 32, sc);
            }
            wg_commit();
        } else {
            wg_fence();
#pragma unroll
            for (int ks = 0; ks < 4; ks++) {
                const int sc = 1;
                wgmma_n192<1, 1>(*(float(*)[96]) & acc[0], da + ks * 128, db + (ks >> 1) * 960 + (ks & 1) * 128, sc);
                wgmma_n48<1, 1>(*(float(*)[24]) & acc[96], da + ks * 128, dr + (ks >> 1) * 960 + (ks & 1) * 32, sc);
            }
            wg_commit();
        }
        wg_wait<1>();
        if (it > 0 && !hold) release(it - 1);
    }
    if (wg == 0 && lane == 0) mbar_arrive(BAR(go));
    asm volatile("setmaxnreg.inc.sync.aligned.u32 %0;" ::"n"(R_CONS));
    mbar_wait(BAR(prep), 0);
    const uint32_t ob = layer ^ 1;
    const bool first = (blk == 0 && w == 0);
    const bool sel0 = (2 * q > g), sel1 = (2 * q + 1 > g);
    constexpr float SC = 0.22360679774997896f * 1.4426950408889634f;
    const float m0 = __uint_as_float(lds32(MISC(mean) + 4 * (16 * warp + g))), m1 = __uint_as_float(lds32(MISC(mean) + 4 * (16 * warp + g + 8)));
    uint4 cs[3][5];
    auto cs_load = [&](int p) {
#pragma unroll
        for (int i = 0; i < 5; i++) cs[p][i] = lds128(MISC(cs) + 4 * (80 * p + 20 * q + 4 * i));
    };
    cs_load(1); cs_load(2);
    wg_wait<0>();
    TS(7);
    if (lane == 0) mbar_arrive(BAR(qdone));
    uint32_t ql[10], qh[10], kl[10], kh[10], vl[10], vh[10];
    auto fold = [&](int p, int f, int h) {
        const int j = (f < 8) ? 8 * p + f : 24 + 2 * p + (f - 8);
        const float c0 = __uint_as_float(u4(cs[p][f >> 1], 2 * (f & 1))), c1 = __uint_as_float(u4(cs[p][f >> 1], 2 * (f & 1) + 1));
        const float m = h ? m1 : m0;
        return pack2(fmaf(-m, c0, acc[4 * j + 2 * h]), fmaf(-m, c1, acc[4 * j + 2 * h + 1]));
    };
#pragma unroll
    for (int f = 0; f < 10; f++) { vh[f] = fold(2, f, 1); if (f < A_VLO) vl[f] = fold(2, f, 0); }
#pragma unroll
    for (int f = 0; f < 10; f++) kh[f] = fold(1, f, 1);
#pragma unroll
    for (int f = 0; f < A_VLO; f++) asm volatile("" : "+r"(vl[f]));
    {
        const uint32_t mk = w == 3 ? 1u : 0u;
        auto mark = [&](uint32_t& v) { v = (v & ~mk) | (ob & mk); };
        mark(kh[0]); mark(kh[5]); mark(vh[0]); mark(vh[4]); mark(vh[8]);
    }
    if (w == 3) {
        uint4* hp = &g_halo[bx][wg][0][lane];
        st_ll4(hp, kh[0], kh[1], kh[3], kh[4]); st_ll4(hp + 32, kh[5], kh[6], kh[8], kh[9]);
        st_ll4(hp + 64, vh[0], vh[1], vh[2], vh[3]); st_ll4(hp + 96, vh[4], vh[5], vh[6], vh[7]);
        st_ll4(hp + 128, vh[8], vh[9], kh[2], kh[7]);
    } else {
        const uint32_t a = sb + Q_EOFF + wg * 8192 + w * Q_ESLOT + mj * Q_EROW + mi * 16;
        stsm_x4(a, kh[0], kh[1], kh[3], kh[4]);
        stsm_x4(a + 64, kh[5], kh[6], kh[8], kh[9]);
        stsm_x4(a + 128, vh[0], vh[1], vh[2], vh[3]);
        stsm_x4(a + 192, vh[4], vh[5], vh[6], vh[7]);
        stsm_x4(a + 256, vh[8], vh[9], kh[2], kh[7]);
        __syncwarp();
        if (lane == 0) mbar_arrive(BAR(ex) + 8 * warp);
    }
    TS(9);
    cs_load(0);
#pragma unroll
    for (int f = 0; f < 10; f++) { kl[f] = fold(1, f, 0); if (f >= A_VLO) vl[f] = fold(2, f, 0); }
#pragma unroll
    for (int f = 0; f < 10; f++) { ql[f] = fold(0, f, 0); qh[f] = fold(0, f, 1); }
    auto rs = [&](int i) { return __uint_as_float(lds32(MISC(rstd) + 4 * (72 * wg + 16 * w + i))); };
    const float kx0 = rs(2 * q + (sel0 ? 0 : 8)), kx1 = rs(2 * q + (sel1 ? 1 : 9)), ky0 = rs(2 * q + (sel0 ? 8 : 16)), ky1 = rs(2 * q + (sel1 ? 9 : 17));
    const float rx = SC * rs(8 + g), ry = SC * rs(16 + g), cx0 = rx * kx0, cx1 = rx * kx1, cy0 = ry * ky0, cy1 = ry * ky1;
    uint4 hv[5];
    const uint4* hp = &g_halo[bx - 1][wg][0][lane];
    auto prev = [&] {
        if (w > 0) {
            const uint32_t a = sb + Q_EOFF + wg * 8192 + (w - 1) * Q_ESLOT + mj * Q_EROW + mi * 16;
            mbar_wait(BAR(ex) + 8 * (warp - 1), 0);
            ldsm_x4(hv[0].x, hv[0].y, hv[0].z, hv[0].w, a);
            ldsm_x4(hv[1].x, hv[1].y, hv[1].z, hv[1].w, a + 64);
            ldsm_x4_t(hv[2].x, hv[2].y, hv[2].z, hv[2].w, a + 128);
            ldsm_x4_t(hv[3].x, hv[3].y, hv[3].z, hv[3].w, a + 192);
            ldsm_x2_t(hv[4].x, hv[4].y, a + 256);
            ldsm_x2(hv[4].z, hv[4].w, a + 288 - (lane >> 4) * 32);
        } else if (blk > 0) {
#pragma unroll
            for (int f = 0; f < 5; f++) hv[f] = ld_ll4(hp + 32 * f);
        } else {
#pragma unroll
            for (int f = 0; f < 5; f++) hv[f] = make_uint4(0, 0, 0, 0);
        }
    };
    uint32_t vt[10][2];
#pragma unroll
    for (int f = 0; f < 10; f++) { vt[f][0] = movm_t(vl[f]); vt[f][1] = movm_t(vh[f]); }
    prev();
    TS(10);
    auto FA = [](int h) { return h == 0 ? 0 : h == 1 ? 3 : h == 2 ? 5 : 8; };
    auto FH = [](int h) { return h < 2 ? 2 : 7; };
    const uint32_t pm = (sel0 ? 0xFFFFu : 0u) | (sel1 ? 0xFFFF0000u : 0u);
    auto softmax = [&](float x0, float x1, float k0, float k1) {
        float mx = fmaxf(x0, x1);
        mx = fmaxf(mx, __shfl_xor_sync(~0u, mx, 1));
        mx = fmaxf(mx, __shfl_xor_sync(~0u, mx, 2));
        x0 = ex2(x0 - mx); x1 = ex2(x1 - mx);
        float sx = x0 + x1;
        sx += __shfl_xor_sync(~0u, sx, 1);
        sx += __shfl_xor_sync(~0u, sx, 2);
        const float ix = frcp(sx);
        return pack2(x0 * k0 * ix, x1 * k1 * ix);
    };
    uint32_t qm[4][2], py[4];
    float sl[4][2];
#pragma unroll
    for (int h = 0; h < 4; h++) {
        const int fa = FA(h), fb = fa + 1, fh = FH(h);
        const bool mine = (h & 1) ? (q >= 2) : (q < 2);
        qm[h][0] = mine ? ql[fh] : 0u; qm[h][1] = mine ? qh[fh] : 0u;
        float S1[4] = {0.f, 0.f, 0.f, 0.f}, S2[4] = {0.f, 0.f, 0.f, 0.f};
        mma16816(S1, ql[fa], qh[fa], ql[fb], qh[fb], kl[fa], kl[fb]); mma1688(S1, qm[h][0], qm[h][1], kl[fh]);
        mma16816(S2, ql[fa], qh[fa], ql[fb], qh[fb], kh[fa], kh[fb]); mma1688(S2, qm[h][0], qm[h][1], kh[fh]);
        sl[h][0] = S1[0]; sl[h][1] = S1[1];
        py[h] = softmax((sel0 ? S1[2] : S2[2]) * cy0, (sel1 ? S1[3] : S2[3]) * cy1, ky0, ky1);
    }
    TS(11);
    if (w == 0 && blk > 0) {
        ll_check5(hv, hp, ob);
#pragma unroll
        for (int f = 2; f < 4; f++) hv[f] = make_uint4(movm_t(hv[f].x), movm_t(hv[f].y), movm_t(hv[f].z), movm_t(hv[f].w));
        hv[4].x = movm_t(hv[4].x); hv[4].y = movm_t(hv[4].y);
    }
    const uint32_t kp[10] = {hv[0].x, hv[0].y, hv[4].z, hv[0].z, hv[0].w, hv[1].x, hv[1].y, hv[4].w, hv[1].z, hv[1].w};
    const uint32_t vp[10] = {hv[2].x, hv[2].y, hv[2].z, hv[2].w, hv[3].x, hv[3].y, hv[3].z, hv[3].w, hv[4].x, hv[4].y};
    TS(12);
    const uint4 ko[2] = {ldg_tab(16, tid & 127), ldg_tab(17, tid & 127)};
    const float bx0 = first && sel0 ? -INFINITY : 0.f, bx1 = first && sel1 ? -INFINITY : 0.f;
    float oacc[10][4];
#pragma unroll
    for (int h = 0; h < 4; h++) {
        const int fa = FA(h), fb = fa + 1, fh = FH(h);
        const bool mine = (h & 1) ? (q >= 2) : (q < 2);
        float S0[4] = {0.f, 0.f, 0.f, 0.f};
        mma16816(S0, ql[fa], qh[fa], ql[fb], qh[fb], kp[fa], kp[fb]); mma1688(S0, qm[h][0], qm[h][1], kp[fh]);
        const uint32_t px = softmax(fmaf(sel0 ? S0[0] : sl[h][0], cx0, bx0), fmaf(sel1 ? S0[1] : sl[h][1], cx1, bx1), kx0, kx1);
#pragma unroll
        for (int i = 0; i < 3; i++) {
            const int f = (i == 0) ? fa : (i == 1) ? fb : fh;
            float O[4] = {0.f, 0.f, 0.f, 0.f};
            mma16816(O, px & ~pm, py[h] & pm, 0u, py[h] & ~pm, vt[f][0], vt[f][1]);
            mma1688(O, px & pm, 0u, vp[f]);
            if (i < 2 || !(h & 1) || mine) { oacc[f][0] = O[0]; oacc[f][1] = O[1]; oacc[f][2] = O[2]; oacc[f][3] = O[3]; }
        }
    }
    TS(13);
    float aw[40];
    uint4 of[5];
    const uint32_t fb = EPOCH ^ ob;
    {
        const uint32_t mk[2] = {q == ((2 * w) & 3), q == ((2 * w + 1) & 3)};
        uint32_t* dst = &g_of[hg][blk][640 * wg + 16 * w].x + lane;
#pragma unroll
        for (int i = 0; i < 20; i++) {
            const uint32_t v = (pack2(oacc[i >> 1][2 * (i & 1)], oacc[i >> 1][2 * (i & 1) + 1]) & ~mk[i & 1]) | (fb & mk[i & 1]);
            u4r(of[i >> 2], i & 3) = v;
            asm volatile("st.relaxed.gpu.global.u32 [%0], %1;" ::"l"(dst + 256 * (i >> 1) + 32 * (i & 1)), "r"(v) : "memory");
        }
        if (lane == 0) mbar_arrive(BAR(att) + 8 * wg);
        TS(14);
    }
    named_bar(1 + wg, 128);
    kernel_stage<2>(ko, sb + Q_KDUMP + 2 * wg * KG_RES, MISC(kg), 2 * wg, sb + F_EO + wg * 8192, w, lane);
    TS(15);
    uint32_t res[20];
    mbar_wait(BAR(res), 0);
    const uint32_t ta = (8 * (mi >> 1) + mj) * 128 + (((2 * w + (mi & 1)) ^ mj) << 4);
    if (layer == 0) {
        const int tok = 16 * w + 8 * (mi & 1) + mj;
#pragma unroll
        for (int k = 0; k < 4; k++)
            ldsm_x4(res[4 * k], res[4 * k + 1], res[4 * k + 2], res[4 * k + 3], sb + W_RES + wg * 10240 + tok * 128 + (((2 * k + (mi >> 1)) ^ mj) << 4));
        ldsm_x4(res[16], res[17], res[18], res[19], sb + W_RES + wg * 10240 + 8192 + tok * 32 + (((mi >> 1) ^ (mj >> 2)) << 4));
    } else {
#pragma unroll
        for (int k = 0; k < 5; k++) ldsm_x4_t(res[4 * k], res[4 * k + 1], res[4 * k + 2], res[4 * k + 3], sb + W_RES + wg * 10240 + k * 2048 + ta);
    }
    fence_async_smem();
    __syncwarp();
    if (lane == 0) mbar_arrive(MISC(ob) + 96 * wg + 64);
    {
#pragma unroll
        for (int i = 0; i < 20; i++) { aw[2 * i] = bf_lo(res[i]); aw[2 * i + 1] = bf_hi(res[i]); }
        mbar_wait(BAR(wfull), 0);
        const uint64_t dm = mkdesc(sb + w_grp(0), 1280, 128, 0);
        wg_fence();
#pragma unroll
        for (int k = 0; k < 5; k++) wgmma_rs80(aw, of[k], dm + k * 160, 1);
        wg_commit();
    }
    conv_tables();
    wg_wait<0>();
    TS(8);
    const uint32_t ck = mi * 1024 + (2 * w + (g & 1)) * 128 + q * 32 + (mi & 1) * 16 + ((2 * w + (g & 1)) & 3) * 4;
    uint32_t bar = MISC(ob) + 96 * wg + 8;
    uint64_t dm = mkdesc(sb + w_grp(1), 1280, 128, 0);
    const uint64_t d0 = mkdesc(sb + o_slot(wg, 0), 1024, 128, 0);
#pragma unroll 1
    for (int j = 1; j < 8; j++, bar += 8, dm += 800) {
        const uint32_t so = (j & 3) * 20480, a = sb + o_slot(wg, 0) + so + ck;
        mbar_wait(bar, layer);
        if (__any_sync(~0u, miss(miss(miss(0, lds32(a), fb), lds32(a + 4096), fb), lds32(a + 8192 - (mi & 2) * 1024), fb) & 1u)) {
            const uint32_t* src = &g_of[osrc_of(j)][blk][640 * wg + 16 * w].x + lane;
#pragma unroll 1
            for (int i = 0, spin = 0; i < 10;) {
                uint32_t v[4];
#pragma unroll
                for (int k = 0; k < 4; k++) asm volatile("ld.relaxed.gpu.global.u32 %0, [%1];" : "=r"(v[k]) : "l"(src + 256 * (i + (k >> 1)) + 32 * (k & 1)) : "memory");
                const int h = q ^ ((2 * w) & 3);
                if (__any_sync(~0u, h < 2 && (miss(miss(0, h ? v[1] : v[0], fb), h ? v[3] : v[2], fb) & 1u)) && ++spin < (1 << 18)) continue;
#pragma unroll
                for (int k = 0; k < 4; k++) sts32(sb + o_slot(wg, 0) + so + (i + (k >> 1)) * 1024 + (2 * w + (k & 1)) * 128 + lane * 4, v[k]);
                i += 2;
            }
            fence_async_smem();
            __syncwarp();
        }
        if (j == 1) TS(17);
        if (j == 5) TS(18);
        const uint64_t da = d0 + (so >> 4);
        wg_fence();
#pragma unroll
        for (int k = 0; k < 5; k++) wgmma_ss80(aw, da + k * 128, dm + k * 160);
        wg_commit();
        wg_wait<1>();
        if (j > 1 && j < 5 && lane == 0) mbar_arrive(bar + 56);
    }
    if (lane == 0) mbar_arrive(BAR(soon) + 8 * wg);
    named_bar(1 + wg, 128);
    wg_wait<0>();
    TS(19);
    {
        float a[2][4] = {{0.f, 0.f, 0.f, 0.f}, {0.f, 0.f, 0.f, 0.f}};
#pragma unroll
        for (int i = 0; i < 40; i++) { a[i & 1][i & 2] += aw[i]; a[i & 1][(i & 2) + 1] = fmaf(aw[i], aw[i], a[i & 1][(i & 2) + 1]); }
#pragma unroll
        for (int j = 0; j < 4; j++) { a[0][j] += a[1][j]; a[0][j] += __shfl_xor_sync(~0u, a[0][j], 1); a[0][j] += __shfl_xor_sync(~0u, a[0][j], 2); }
        if (q == 0) st_ll4(&g_sp2[blk][warp][hg][g], (__float_as_uint(a[0][0]) & ~1u) | ob, __float_as_uint(a[0][1]), __float_as_uint(a[0][2]), __float_as_uint(a[0][3]));
    }
    TS(23);
#pragma unroll
    for (int i = 0; i < 20; i++) res[i] = pack2(aw[2 * i], aw[2 * i + 1]);
    {
        const uint32_t mk = (g & 3) ? 0u : 0x00010001u;
#pragma unroll
        for (int k = 0; k < 5; k++) {
            uint32_t m[4];
#pragma unroll
            for (int i = 0; i < 4; i++) m[i] = (res[4 * k + i] & ~mk) | (mk & (0u - ob));
            stsm_x4_t(sb + w_out(wg) + k * 2048 + ta, m[0], m[1], m[2], m[3]);
        }
        fence_async_smem();
        named_bar(1 + wg, 128);
        if (w == 0 && elect_one()) {
            asm volatile("cp.async.bulk.tensor.2d.global.shared::cta.bulk_group [%0, {%2, %3}], [%1];"
                         ::"l"(TMAP(7)), "r"(sb + w_out(wg)), "r"(1024 * wg + 64 * blk), "r"(hg * 80) : "memory");
            bulk_commit();
            mbar_arrive(BAR(staged));
        }
        __syncwarp();
        TS(20);
    }
    if (layer) {
#pragma unroll
        for (int k = 0; k < 5; k++) stsm_x4_t(sb + W_RES + wg * 10240 + k * 2048 + ta, res[4 * k], res[4 * k + 1], res[4 * k + 2], res[4 * k + 3]);
    }
    TS(22);
    TS_PHASE(2 * layer + 1);
    TS(0);
    indices();
    conv_wg<2>(cta_channel(bx, 2 * (warp >> 2)), layer, sb + F_EO + (warp >> 2) * 8192, sb + (1 + 2 * (warp >> 2)) * Q_SB, sb + F_S23, MISC(kg.kexp) + 8 * (warp >> 2),
               MISC(epoch), sb, BAR(st), BAR(fdone0), warp, lane, fa1, ftw, [&] {
        if ((warp & 3) == 0 && elect_one()) {
            asm volatile("cp.async.bulk.wait_group.read 0;" ::: "memory");
            if (layer == 0) { mbar_arrive_cta(BAR(wfree), 0); mbar_arrive_cta(BAR(wfree), 1); }
        }
        __syncwarp();
        if (warp < 4) mbar_wait(BAR(staged), 0);
    }, [&] {
        if (layer == 0 && warp >= 4 && elect_one()) {
            mbar_wait(BAR(wfree), 0);
            issue_w(BAR(full) + sizeof(Bars), warp - 4, 1);
        }
        __syncwarp();
    } TS_PASS);
    __syncwarp();
    if (lane == 0) mbar_arrive(warp < 4 ? BAR(fdone0) : BAR(fdone1));
    TS(20);
    asm volatile("setmaxnreg.dec.sync.aligned.u32 168;");
    }
    named_bar(1 + (warp >> 2), 128);
    asm volatile("setmaxnreg.dec.sync.aligned.u32 %0;" ::"n"(504 - 2 * R_CONS));
    }
    indices();
    const int cq = 4 * (warp >> 1) + (lane & 3), tg = 8 * (warp & 1) + (lane >> 2);
    const uint32_t fb = ~EPOCH & 1u;
    uint2 xr[4][2];
    __syncthreads();
    if (tid < 320) {
#pragma unroll
        for (int i = 0; i < 8; i++) {
            const int ch = 4 * cq + (i >> 1);
            asm volatile("ld.shared.v2.u32 {%0, %1}, [%2];" : "=r"(xr[i >> 1][i & 1].x), "=r"(xr[i >> 1][i & 1].y)
                         : "r"(sb + W_RES + (i & 1) * 10240 + ch * 128 + (((tg >> 1) ^ (ch & 7)) << 4) + (tg & 1) * 8) : "memory");
        }
    }
    if (tid < 320) {
        const uint4* src = &g_of[hg][blk][64 * cq + tg];
        uint4 v[4];
#pragma unroll
        for (int i = 0; i < 4; i++) v[i] = make_uint4(~fb, ~fb, ~fb, ~fb);
        auto lack = [&](int i) { return miss(0, (warp & 1) ? u4(v[i], 2 * (i & 1) + 1) : u4(v[i], 2 * (i & 1)), fb); };
        int spin = 0;
        while (true) {
#pragma unroll
            for (int i = 0; i < 4; i++) if (lack(i) & 1u) v[i] = ld_ll4(src + 16 * i);
            if (!((lack(0) | lack(1) | lack(2) | lack(3)) & 1u) || ++spin >= (1 << 18)) break;
        }
        TS(21);
#pragma unroll
        for (int i = 0; i < 16; i++) asm("add.rn.bf16x2 %0, %0, %1;" : "+r"(u4r(v[i >> 2], i & 3)) : "r"((i & 1) ? xr[i >> 2][(i >> 1) & 1].y : xr[i >> 2][(i >> 1) & 1].x));
#pragma unroll
        for (int j = 0; j < 8; j++) {
            const uint32_t sel = (j & 2) ? 0x7632 : 0x5410;
            const int k = 2 * (j & 1) + (j >> 2);
            asm volatile("st.shared.v2.u32 [%0], {%1, %2};" ::"r"(sb + 2 * Q_SB + (16 * j + tg) * 160 + cq * 8),
                         "r"(__byte_perm(u4(v[0], k), u4(v[1], k), sel)), "r"(__byte_perm(u4(v[2], k), u4(v[3], k), sel)) : "memory");
        }
        fence_async_smem();
    }
    __syncthreads();
    if (warp == 0 && elect_one()) {
        asm volatile("cp.async.bulk.tensor.3d.global.shared::cta.bulk_group [%0, {%2, %3, 0}], [%1];" ::"l"(TMAP(9)), "r"(sb + 2 * Q_SB), "r"(80 * hg), "r"(16 * blk) : "memory");
        bulk_commit();
        asm volatile("cp.async.bulk.wait_group.read 0;" ::: "memory");
    }
    if (bx == 0 && tid == 0) g_epoch = (EPOCH + 1) & 0x3FFFFFFFu;
    TS(22);
    TS_END;
}
typedef CUresult (*EncodeTiledFn)(CUtensorMap*, CUtensorMapDataType, cuuint32_t, void*, const cuuint64_t*, const cuuint64_t*, const cuuint32_t*,
                                  const cuuint32_t*, CUtensorMapInterleave, CUtensorMapSwizzle, CUtensorMapL2promotion, CUtensorMapFloatOOBfill);

static void make_map(EncodeTiledFn enc, CUtensorMap* m, const void* base, int rank, const cuuint64_t* dims, const cuuint64_t* strides,
                     const cuuint32_t* box, CUtensorMapSwizzle sw) {
    cuuint32_t es[4] = {1, 1, 1, 1};
    enc(m, CU_TENSOR_MAP_DATA_TYPE_BFLOAT16, rank, (void*)base, dims, strides, box, es, CU_TENSOR_MAP_INTERLEAVE_NONE, sw,
        sw == CU_TENSOR_MAP_SWIZZLE_128B ? CU_TENSOR_MAP_L2_PROMOTION_L2_128B : CU_TENSOR_MAP_L2_PROMOTION_NONE, CU_TENSOR_MAP_FLOAT_OOB_FILL_NONE);
}

template <typename... KArgs, typename... Args>
static void launch(void (*kern)(KArgs...), int grid, int block, int smem, int cluster, bool pdl, Args... args) {
    cudaLaunchConfig_t cfg = {};
    cfg.gridDim = dim3(grid); cfg.blockDim = dim3(block); cfg.dynamicSmemBytes = smem; cfg.stream = cudaStreamPerThread;
    cudaLaunchAttribute at[2];
    int n = 0;
    if (cluster > 1) { at[n].id = cudaLaunchAttributeClusterDimension; at[n].val.clusterDim.x = cluster; at[n].val.clusterDim.y = 1; at[n].val.clusterDim.z = 1; n++; }
    if (pdl) { at[n].id = cudaLaunchAttributeProgrammaticStreamSerialization; at[n].val.programmaticStreamSerializationAllowed = 1; n++; }
    cfg.attrs = at; cfg.numAttrs = n;
    cudaLaunchKernelEx(&cfg, kern, KArgs(args)...);
}

struct HostState {
    bool ready = false;
    const void* key[4] = {nullptr, nullptr, nullptr, nullptr};
    CUtensorMap mX[2], mRes[2], mW, mWr, mWo, mOut, mFin, mResA;
    bf16 *x1T, *x2T;
    unsigned* epoch;
};

extern "C" void kernel_launch(void* const* d_in, const int* in_sizes, int n_in, void* d_out, int out_size) {
    const bf16* x = (const bf16*)d_in[0];
    const bf16* wqkv = (const bf16*)d_in[1];
    const bf16* wo = (const bf16*)d_in[2];
    const bf16* lar = (const bf16*)d_in[4];
    const bf16* aim = (const bf16*)d_in[5];
    const bf16* cre = (const bf16*)d_in[6];
    const bf16* cim = (const bf16*)d_in[7];
    const bf16* logdt = (const bf16*)d_in[8];
    const bf16* dskip = (const bf16*)d_in[9];
    static HostState hs;
    if (!hs.ready || hs.key[0] != wqkv || hs.key[1] != wo || hs.key[2] != x || hs.key[3] != d_out) {
        void* fn = nullptr;
        cudaDriverEntryPointQueryResult qr;
        cudaGetDriverEntryPoint("cuTensorMapEncodeTiled", &fn, cudaEnableDefault, &qr);
        EncodeTiledFn enc = (EncodeTiledFn)fn;
        cudaGetSymbolAddress((void**)&hs.epoch, g_epoch);
        cudaGetSymbolAddress((void**)&hs.x1T, g_x1T);
        cudaGetSymbolAddress((void**)&hs.x2T, g_x2T);
        {
            cuuint64_t d[3] = {DM, SEQ / 2, 2}, s[2] = {DM * 4, DM * 2};
            cuuint32_t b[3] = {64, 64, 2}, ba[3] = {64, 64, 1}, br[3] = {16, 64, 1};
            make_map(enc, &hs.mX[0], x, 3, d, s, b, CU_TENSOR_MAP_SWIZZLE_128B);
            make_map(enc, &hs.mResA, x, 3, d, s, ba, CU_TENSOR_MAP_SWIZZLE_128B);
            make_map(enc, &hs.mRes[0], x, 3, d, s, br, CU_TENSOR_MAP_SWIZZLE_32B);
            cuuint64_t d2[3] = {SEQ / 2, DM, 2}, s2[2] = {XP * 2, SEQ};
            cuuint32_t b2[3] = {64, 80, 2};
            make_map(enc, &hs.mX[1], hs.x2T, 3, d2, s2, b, CU_TENSOR_MAP_SWIZZLE_128B);
            make_map(enc, &hs.mRes[1], hs.x2T, 3, d2, s2, b2, CU_TENSOR_MAP_SWIZZLE_128B);
            cuuint64_t d3[2] = {SEQ, DM};
            make_map(enc, &hs.mOut, hs.x1T, 2, d3, s2, b2, CU_TENSOR_MAP_SWIZZLE_128B);
        }
        { cuuint64_t d[2] = {3 * DM, DM}, s[1] = {3 * DM * 2}; cuuint32_t b[2] = {64, 32};
          make_map(enc, &hs.mW, wqkv, 2, d, s, b, CU_TENSOR_MAP_SWIZZLE_128B); }
        { cuuint64_t d[3] = {DM, DM, 3}, s[2] = {3 * DM * 2, DM * 2}; cuuint32_t b[3] = {16, 32, 3};
          make_map(enc, &hs.mWr, wqkv, 3, d, s, b, CU_TENSOR_MAP_SWIZZLE_32B); }
        { cuuint64_t d[4] = {8, 8, DM / 8, DM / 8}, s[3] = {DM * 2, 16, DM * 16}; cuuint32_t b[4] = {8, 8, 10, 5};
          make_map(enc, &hs.mWo, wo, 4, d, s, b, CU_TENSOR_MAP_SWIZZLE_NONE); }
        { cuuint64_t d[3] = {DM, SEQ / 8, 8}, s[2] = {DM * 16, DM * 2}; cuuint32_t b[3] = {80, 16, 8};
          make_map(enc, &hs.mFin, d_out, 3, d, s, b, CU_TENSOR_MAP_SWIZZLE_NONE); }
        cudaFuncSetAttribute(fused_kernel, cudaFuncAttributeMaxDynamicSharedMemorySize, Q_SMEM);
        hs.key[0] = wqkv; hs.key[1] = wo; hs.key[2] = x; hs.key[3] = d_out;
        hs.ready = true;
    }
    const SsmParams sp = {lar, aim, cre, cim, logdt, dskip, hs.epoch};
    launch(fused_kernel, 128, 384, Q_SMEM, 2, false, sp, hs.mX[0], hs.mX[1], hs.mW, hs.mWr, hs.mRes[0], hs.mRes[1], hs.mOut, hs.mWo, hs.mFin, hs.mResA);
}
```

```cpp
#include <cuda_runtime.h>
#include <cuda.h>
#include <cuda_bf16.h>
#include <cuda_fp16.h>
#include <stdint.h>

typedef __nv_bfloat16 bf16;

constexpr int SEQ = 2048;
constexpr int DM  = 640;
constexpr int XP  = SEQ + 64;
constexpr int NMODE = 192;
#define HINT_SPINS (1 << 18)

__device__ __forceinline__ uint32_t s2u(const void* p) { return (uint32_t)__cvta_generic_to_shared(p); }
__device__ __forceinline__ void mbar_init(uint32_t b, int c) { asm volatile("mbarrier.init.shared::cta.b64 [%0], %1;" ::"r"(b), "r"(c)); }
__device__ __forceinline__ void mbar_expect(uint32_t b, uint32_t bytes) { asm volatile("mbarrier.arrive.expect_tx.shared::cta.b64 _, [%0], %1;" ::"r"(b), "r"(bytes) : "memory"); }
__device__ __forceinline__ void mbar_arrive(uint32_t b) { asm volatile("mbarrier.arrive.shared::cta.b64 _, [%0];" ::"r"(b) : "memory"); }
__device__ __forceinline__ void mbar_arrive_cta(uint32_t b, uint32_t cta) {
    asm volatile("{\n.reg .b32 ra;\nmapa.shared::cluster.u32 ra, %0, %1;\nmbarrier.arrive.shared::cluster.b64 _, [ra];\n}" ::"r"(b), "r"(cta) : "memory");
}
__device__ __forceinline__ void mbar_wait(uint32_t b, uint32_t ph) {
#ifdef M_SAFE
    asm volatile("{\n.reg .pred p;\n.reg .u32 n;\nmbarrier.try_wait.parity.shared::cta.b64 p, [%0], %1;\n@p bra D;\nmov.u32 n, 0;\n"
                 "W: mbarrier.try_wait.parity.shared::cta.b64 p, [%0], %1;\n@p bra D;\nadd.u32 n, n, 1;\nsetp.lt.u32 p, n, 4194304;\n@p bra W;\ntrap;\nD:\n}"
                 ::"r"(b), "r"(ph) : "memory");
#else
    asm volatile("{\n.reg .pred p;\nW: mbarrier.try_wait.parity.shared::cta.b64 p, [%0], %1;\n@!p bra W;\n}" ::"r"(b), "r"(ph) : "memory");
#endif
}
__device__ __forceinline__ void fence_mbar_init() { asm volatile("fence.mbarrier_init.release.cluster;" ::: "memory"); }
__device__ __forceinline__ void cluster_sync() { asm volatile("barrier.cluster.arrive.aligned;\nbarrier.cluster.wait.aligned;" ::: "memory"); }
__device__ __forceinline__ void pdl_wait() { asm volatile("griddepcontrol.wait;" ::: "memory"); }
__device__ __forceinline__ void pdl_launch() { asm volatile("griddepcontrol.launch_dependents;" ::: "memory"); }
__device__ __forceinline__ void named_bar(int id, int n) { asm volatile("bar.sync %0, %1;" ::"r"(id), "r"(n) : "memory"); }
__device__ __forceinline__ void fence_async_smem() { asm volatile("fence.proxy.async.shared::cta;" ::: "memory"); }

__device__ __forceinline__ void tma2d(uint32_t dst, const CUtensorMap* m, int c0, int c1, uint32_t bar) {
    asm volatile("cp.async.bulk.tensor.2d.shared::cluster.global.mbarrier::complete_tx::bytes [%0], [%1, {%3, %4}], [%2];"
                 ::"r"(dst), "l"(m), "r"(bar), "r"(c0), "r"(c1) : "memory");
}
__device__ __forceinline__ void tma2d_mc(uint32_t dst, const CUtensorMap* m, int c0, int c1, uint32_t bar, uint16_t mask) {
    asm volatile("cp.async.bulk.tensor.2d.shared::cluster.global.mbarrier::complete_tx::bytes.multicast::cluster [%0], [%1, {%3, %4}], [%2], %5;"
                 ::"r"(dst), "l"(m), "r"(bar), "r"(c0), "r"(c1), "h"(mask) : "memory");
}
__device__ __forceinline__ void tma3d(uint32_t dst, const CUtensorMap* m, int c0, int c1, int c2, uint32_t bar) {
    asm volatile("cp.async.bulk.tensor.3d.shared::cluster.global.mbarrier::complete_tx::bytes [%0], [%1, {%3, %4, %5}], [%2];"
                 ::"r"(dst), "l"(m), "r"(bar), "r"(c0), "r"(c1), "r"(c2) : "memory");
}
__device__ __forceinline__ void tma3d_mc(uint32_t dst, const CUtensorMap* m, int c0, int c1, int c2, uint32_t bar, uint16_t mask) {
    asm volatile("cp.async.bulk.tensor.3d.shared::cluster.global.mbarrier::complete_tx::bytes.multicast::cluster [%0], [%1, {%3, %4, %5}], [%2], %6;"
                 ::"r"(dst), "l"(m), "r"(bar), "r"(c0), "r"(c1), "r"(c2), "h"(mask) : "memory");
}
__device__ __forceinline__ void bulk_g2s(uint32_t dst, const void* src, uint32_t bytes, uint32_t bar) {
    asm volatile("cp.async.bulk.shared::cluster.global.mbarrier::complete_tx::bytes [%0], [%1], %2, [%3];"
                 ::"r"(dst), "l"(src), "r"(bytes), "r"(bar) : "memory");
}
__device__ __forceinline__ void bulk_g2s_mc(uint32_t dst, const void* src, uint32_t bytes, uint32_t bar, uint16_t mask) {
    asm volatile("cp.async.bulk.shared::cluster.global.mbarrier::complete_tx::bytes.multicast::cluster [%0], [%1], %2, [%3], %4;"
                 ::"r"(dst), "l"(src), "r"(bytes), "r"(bar), "h"(mask) : "memory");
}
__device__ __forceinline__ void prefetch_l2(const void* p, uint32_t bytes) { asm volatile("cp.async.bulk.prefetch.L2.global [%0], %1;" ::"l"(p), "r"(bytes) : "memory"); }
__device__ __forceinline__ void prefetch_tmap(const CUtensorMap* m) { asm volatile("prefetch.tensormap [%0];" ::"l"(m) : "memory"); }

__device__ __forceinline__ void wg_fence() { asm volatile("wgmma.fence.sync.aligned;" ::: "memory"); }
__device__ __forceinline__ void wg_commit() { asm volatile("wgmma.commit_group.sync.aligned;" ::: "memory"); }
template <int N> __device__ __forceinline__ void wg_wait() { asm volatile("wgmma.wait_group.sync.aligned %0;" ::"n"(N) : "memory"); }
__device__ __forceinline__ uint64_t mkdesc(uint32_t addr, uint32_t lbo, uint32_t sbo, uint32_t mode) {
    return (uint64_t)((addr & 0x3FFFF) >> 4) | ((uint64_t)(lbo >> 4) << 16) | ((uint64_t)(sbo >> 4) << 32) | ((uint64_t)mode << 62);
}

__device__ __forceinline__ void mma16816(float (&c)[4], uint32_t a0, uint32_t a1, uint32_t a2, uint32_t a3, uint32_t b0, uint32_t b1) {
    asm("mma.sync.aligned.m16n8k16.row.col.f32.bf16.bf16.f32 {%0,%1,%2,%3},{%4,%5,%6,%7},{%8,%9},{%0,%1,%2,%3};"
                 : "+f"(c[0]), "+f"(c[1]), "+f"(c[2]), "+f"(c[3]) : "r"(a0), "r"(a1), "r"(a2), "r"(a3), "r"(b0), "r"(b1));
}
__device__ __forceinline__ void mma1688(float (&c)[4], uint32_t a0, uint32_t a1, uint32_t b0) {
    asm("mma.sync.aligned.m16n8k8.row.col.f32.bf16.bf16.f32 {%0,%1,%2,%3},{%4,%5},{%6},{%0,%1,%2,%3};"
                 : "+f"(c[0]), "+f"(c[1]), "+f"(c[2]), "+f"(c[3]) : "r"(a0), "r"(a1), "r"(b0));
}
__device__ __forceinline__ void ldsm_x4(uint32_t& r0, uint32_t& r1, uint32_t& r2, uint32_t& r3, uint32_t a) {
    asm volatile("ldmatrix.sync.aligned.m8n8.x4.shared.b16 {%0,%1,%2,%3}, [%4];" : "=r"(r0), "=r"(r1), "=r"(r2), "=r"(r3) : "r"(a) : "memory");
}
__device__ __forceinline__ void ldsm_x4_t(uint32_t& r0, uint32_t& r1, uint32_t& r2, uint32_t& r3, uint32_t a) {
    asm volatile("ldmatrix.sync.aligned.m8n8.x4.trans.shared.b16 {%0,%1,%2,%3}, [%4];" : "=r"(r0), "=r"(r1), "=r"(r2), "=r"(r3) : "r"(a) : "memory");
}
__device__ __forceinline__ void ldsm_x2(uint32_t& r0, uint32_t& r1, uint32_t a) {
    asm volatile("ldmatrix.sync.aligned.m8n8.x2.shared.b16 {%0,%1}, [%2];" : "=r"(r0), "=r"(r1) : "r"(a) : "memory");
}
__device__ __forceinline__ void ldsm_x2_t(uint32_t& r0, uint32_t& r1, uint32_t a) {
    asm volatile("ldmatrix.sync.aligned.m8n8.x2.trans.shared.b16 {%0,%1}, [%2];" : "=r"(r0), "=r"(r1) : "r"(a) : "memory");
}
__device__ __forceinline__ void stsm_x4(uint32_t a, uint32_t r0, uint32_t r1, uint32_t r2, uint32_t r3) {
    asm volatile("stmatrix.sync.aligned.m8n8.x4.shared.b16 [%0], {%1,%2,%3,%4};" ::"r"(a), "r"(r0), "r"(r1), "r"(r2), "r"(r3) : "memory");
}
__device__ __forceinline__ void stsm_x4_t(uint32_t a, uint32_t r0, uint32_t r1, uint32_t r2, uint32_t r3) {
    asm volatile("stmatrix.sync.aligned.m8n8.x4.trans.shared.b16 [%0], {%1,%2,%3,%4};" ::"r"(a), "r"(r0), "r"(r1), "r"(r2), "r"(r3) : "memory");
}
__device__ __forceinline__ void stsm_x2(uint32_t a, uint32_t r0, uint32_t r1) {
    asm volatile("stmatrix.sync.aligned.m8n8.x2.shared.b16 [%0], {%1,%2};" ::"r"(a), "r"(r0), "r"(r1) : "memory");
}
__device__ __forceinline__ uint32_t movm_t(uint32_t a) {
    uint32_t d;
    asm volatile("movmatrix.sync.aligned.m8n8.trans.b16 %0, %1;" : "=r"(d) : "r"(a));
    return d;
}
__device__ __forceinline__ uint32_t lds32(uint32_t a) { uint32_t v; asm volatile("ld.shared.u32 %0, [%1];" : "=r"(v) : "r"(a) : "memory"); return v; }
__device__ __forceinline__ uint32_t ldsv32(uint32_t a) { uint32_t v; asm volatile("ld.volatile.shared.u32 %0, [%1];" : "=r"(v) : "r"(a) : "memory"); return v; }
__device__ __forceinline__ void sts32(uint32_t a, uint32_t v) { asm volatile("st.shared.u32 [%0], %1;" ::"r"(a), "r"(v) : "memory"); }
__device__ __forceinline__ uint4 lds128(uint32_t a) { uint4 v; asm volatile("ld.shared.v4.u32 {%0,%1,%2,%3}, [%4];" : "=r"(v.x), "=r"(v.y), "=r"(v.z), "=r"(v.w) : "r"(a) : "memory"); return v; }
__device__ __forceinline__ void sts128(uint32_t a, uint4 v) { asm volatile("st.shared.v4.u32 [%0], {%1,%2,%3,%4};" ::"r"(a), "r"(v.x), "r"(v.y), "r"(v.z), "r"(v.w) : "memory"); }

__device__ __forceinline__ void stg128(void* p, uint4 v) { asm volatile("st.global.v4.u32 [%0], {%1,%2,%3,%4};" ::"l"(p), "r"(v.x), "r"(v.y), "r"(v.z), "r"(v.w) : "memory"); }

__device__ __forceinline__ uint4 ldg128(const void* p) { uint4 v; asm volatile("ld.global.v4.u32 {%0,%1,%2,%3}, [%4];" : "=r"(v.x), "=r"(v.y), "=r"(v.z), "=r"(v.w) : "l"(p) : "memory"); return v; }
__device__ __forceinline__ uint2 ldg64(const void* p) { uint2 v; asm volatile("ld.global.v2.u32 {%0,%1}, [%2];" : "=r"(v.x), "=r"(v.y) : "l"(p) : "memory"); return v; }
__device__ __forceinline__ uint32_t ldg32(const void* p) { uint32_t v; asm volatile("ld.global.u32 %0, [%1];" : "=r"(v) : "l"(p) : "memory"); return v; }

__device__ __forceinline__ uint32_t pack2(float lo, float hi) {
    uint32_t r;
    asm("cvt.rn.bf16x2.f32 %0, %1, %2;" : "=r"(r) : "f"(hi), "f"(lo));
    return r;
}
__device__ __forceinline__ float bf_lo(uint32_t v) { return __uint_as_float(v << 16); }
__device__ __forceinline__ float bf_hi(uint32_t v) { return __uint_as_float(v & 0xFFFF0000u); }
__device__ __forceinline__ float rbf(float x) { return __uint_as_float(pack2(0.f, x) & 0xFFFF0000u); }
__device__ __forceinline__ float ex2(float x) { float r; asm("ex2.approx.ftz.f32 %0, %1;" : "=f"(r) : "f"(x)); return r; }

__device__ __forceinline__ float2 ln_finish(float sum, float sumsq) {
    const float m = sum * (1.0f / DM);
    const float v = fmaxf(fmaf(sumsq, 1.0f / DM, -m * m), 0.f);
    float s, r;
    asm("sqrt.approx.ftz.f32 %0, %1;" : "=f"(s) : "f"(rbf(rbf(v) + 1e-5f)));
    asm("rcp.approx.ftz.f32 %0, %1;" : "=f"(r) : "f"(rbf(s)));
    return make_float2(m, r);
}
__device__ __forceinline__ uint32_t ln_finish_packed(float sum, float sumsq) {
    const float m = sum * (1.0f / DM);
    const float v = fmaxf(fmaf(sumsq, 1.0f / DM, -m * m), 0.f);
    float s;
    asm("sqrt.approx.ftz.f32 %0, %1;" : "=f"(s) : "f"(rbf(rbf(v) + 1e-5f)));
    return pack2(s, m);
}
__device__ __forceinline__ float frsq(float x) { float r; asm("rsqrt.approx.ftz.f32 %0, %1;" : "=f"(r) : "f"(x)); return r; }
__device__ __forceinline__ float frcp(float x) { float r; asm("rcp.approx.ftz.f32 %0, %1;" : "=f"(r) : "f"(x)); return r; }
__device__ __forceinline__ bool elect_one() {
    uint32_t p;
    asm volatile("{\n.reg .pred p;\nelect.sync _|p, 0xffffffff;\nselp.u32 %0, 1, 0, p;\n}" : "=r"(p));
    return p != 0;
}
__device__ __forceinline__ void cluster_arrive_relaxed() { asm volatile("barrier.cluster.arrive.relaxed.aligned;" ::: "memory"); }
__device__ __forceinline__ void cluster_wait() { asm volatile("barrier.cluster.wait.aligned;" ::: "memory"); }
__device__ __forceinline__ uint32_t miss(uint32_t acc, uint32_t v, uint32_t mark) {
    uint32_t r;
    asm("lop3.b32 %0, %1, %2, %3, 0xF6;" : "=r"(r) : "r"(acc), "r"(v), "r"(mark));
    return r;
}
__device__ __forceinline__ unsigned long long ld_ll(const unsigned long long* p) {
    unsigned long long v;
    asm volatile("ld.relaxed.gpu.global.b64 %0, [%1];" : "=l"(v) : "l"(p) : "memory");
    return v;
}
__device__ __forceinline__ void st_ll(unsigned long long* p, uint32_t payload, uint32_t tag) {
    const unsigned long long v = (unsigned long long)payload | ((unsigned long long)tag << 32);
    asm volatile("st.relaxed.gpu.global.b64 [%0], %1;" ::"l"(p), "l"(v) : "memory");
}
__device__ __forceinline__ uint4 ld_ll4(const uint4* p) {
    uint4 v;
    asm volatile("{\n.reg .b128 t;\n.reg .b64 a, b;\nld.relaxed.gpu.global.b128 t, [%4];\nmov.b128 {a, b}, t;\nmov.b64 {%0, %1}, a;\nmov.b64 {%2, %3}, b;\n}"
                 : "=r"(v.x), "=r"(v.y), "=r"(v.z), "=r"(v.w) : "l"(p) : "memory");
    return v;
}
__device__ __forceinline__ void st_ll4(uint4* p, uint32_t x, uint32_t y, uint32_t z, uint32_t w) {
    asm volatile("{\n.reg .b128 t;\n.reg .b64 a, b;\nmov.b64 a, {%1, %2};\nmov.b64 b, {%3, %4};\nmov.b128 t, {a, b};\nst.relaxed.gpu.global.b128 [%0], t;\n}"
                 ::"l"(p), "r"(x), "r"(y), "r"(z), "r"(w) : "memory");
}

__device__ __forceinline__ void bulk_s2g(void* dst, uint32_t src, uint32_t bytes) {
    asm volatile("cp.async.bulk.global.shared::cta.bulk_group [%0], [%1], %2;" ::"l"(dst), "r"(src), "r"(bytes) : "memory");
}
__device__ __forceinline__ void bulk_commit() { asm volatile("cp.async.bulk.commit_group;" ::: "memory"); }
__device__ __forceinline__ void bulk_wait() { asm volatile("cp.async.bulk.wait_group 0;" ::: "memory"); }
__device__ __forceinline__ void fence_async_global() { asm volatile("fence.proxy.async.global;" ::: "memory"); }
__device__ __forceinline__ void fence_release() { asm volatile("fence.release.gpu;" ::: "memory"); }
__device__ __forceinline__ void fence_acquire() { asm volatile("fence.acquire.gpu;" ::: "memory"); }
__device__ __forceinline__ void ll_check5(uint4 (&f)[5], const uint4* p, uint32_t mark) {
#define LL_LD(i, a, b, c, d) "ld.relaxed.gpu.global.b128 q, [%20 + " #i "];\nmov.b128 {u, v}, q;\nmov.b64 {%" #a ", %" #b "}, u;\nmov.b64 {%" #c ", %" #d "}, v;\n"
    asm volatile("{\n.reg .pred p;\n.reg .b32 t, n, m;\n.reg .b128 q;\n.reg .b64 u, v;\nmov.u32 n, 0x7FFFF;\n"
                 "L:\nlop3.b32 t, %0, %4, %21, 0x7E;\nlop3.b32 t, t, %8, %21, 0xF6;\nlop3.b32 t, t, %12, %21, 0xF6;\nlop3.b32 t, t, %16, %21, 0xF6;\n"
                 "shr.u32 m, n, 18;\nand.b32 t, t, m;\nsetp.ne.u32 p, t, 0;\nvote.sync.any.pred p, p, 0xffffffff;\n@!p bra.uni D;\n"
                 LL_LD(0, 0, 1, 2, 3) LL_LD(512, 4, 5, 6, 7) LL_LD(1024, 8, 9, 10, 11) LL_LD(1536, 12, 13, 14, 15) LL_LD(2048, 16, 17, 18, 19)
                 "sub.u32 n, n, 1;\nbra.uni L;\nD:\n}"
                 : "+r"(f[0].x), "+r"(f[0].y), "+r"(f[0].z), "+r"(f[0].w), "+r"(f[1].x), "+r"(f[1].y), "+r"(f[1].z), "+r"(f[1].w), "+r"(f[2].x), "+r"(f[2].y),
                   "+r"(f[2].z), "+r"(f[2].w), "+r"(f[3].x), "+r"(f[3].y), "+r"(f[3].z), "+r"(f[3].w), "+r"(f[4].x), "+r"(f[4].y), "+r"(f[4].z), "+r"(f[4].w)
                 : "l"(p), "r"(mark) : "memory");
}
template<int TA, int TB>
__device__ __forceinline__ void wgmma_n192(float (&d)[96], uint64_t da, uint64_t db, int scale_d) {
  asm volatile("{\n.reg .pred p;\nsetp.ne.b32 p, %98, 0;\n"
    "wgmma.mma_async.sync.aligned.m64n192k16.f32.bf16.bf16 "
    "{%0, %1, %2, %3, %4, %5, %6, %7, %8, %9, %10, %11, %12, %13, %14, %15, %16, %17, %18, %19, %20, %21, %22, %23, %24, %25, %26, %27, %28, %29, %30, %31, %32, %33, %34, %35, %36, %37, %38, %39, %40, %41, %42, %43, %44, %45, %46, %47, %48, %49, %50, %51, %52, %53, %54, %55, %56, %57, %58, %59, %60, %61, %62, %63, %64, %65, %66, %67, %68, %69, %70, %71, %72, %73, %74, %75, %76, %77, %78, %79, %80, %81, %82, %83, %84, %85, %86, %87, %88, %89, %90, %91, %92, %93, %94, %95}, %96, %97, p, 1, 1, %99, %100;\n}\n"
    : "+f"(d[0]), "+f"(d[1]), "+f"(d[2]), "+f"(d[3]), "+f"(d[4]), "+f"(d[5]), "+f"(d[6]), "+f"(d[7]), "+f"(d[8]), "+f"(d[9]), "+f"(d[10]), "+f"(d[11]), "+f"(d[12]), "+f"(d[13]), "+f"(d[14]), "+f"(d[15]), "+f"(d[16]), "+f"(d[17]), "+f"(d[18]), "+f"(d[19]), "+f"(d[20]), "+f"(d[21]), "+f"(d[22]), "+f"(d[23]), "+f"(d[24]), "+f"(d[25]), "+f"(d[26]), "+f"(d[27]), "+f"(d[28]), "+f"(d[29]), "+f"(d[30]), "+f"(d[31]), "+f"(d[32]), "+f"(d[33]), "+f"(d[34]), "+f"(d[35]), "+f"(d[36]), "+f"(d[37]), "+f"(d[38]), "+f"(d[39]), "+f"(d[40]), "+f"(d[41]), "+f"(d[42]), "+f"(d[43]), "+f"(d[44]), "+f"(d[45]), "+f"(d[46]), "+f"(d[47]), "+f"(d[48]), "+f"(d[49]), "+f"(d[50]), "+f"(d[51]), "+f"(d[52]), "+f"(d[53]), "+f"(d[54]), "+f"(d[55]), "+f"(d[56]), "+f"(d[57]), "+f"(d[58]), "+f"(d[59]), "+f"(d[60]), "+f"(d[61]), "+f"(d[62]), "+f"(d[63]), "+f"(d[64]), "+f"(d[65]), "+f"(d[66]), "+f"(d[67]), "+f"(d[68]), "+f"(d[69]), "+f"(d[70]), "+f"(d[71]), "+f"(d[72]), "+f"(d[73]), "+f"(d[74]), "+f"(d[75]), "+f"(d[76]), "+f"(d[77]), "+f"(d[78]), "+f"(d[79]), "+f"(d[80]), "+f"(d[81]), "+f"(d[82]), "+f"(d[83]), "+f"(d[84]), "+f"(d[85]), "+f"(d[86]), "+f"(d[87]), "+f"(d[88]), "+f"(d[89]), "+f"(d[90]), "+f"(d[91]), "+f"(d[92]), "+f"(d[93]), "+f"(d[94]), "+f"(d[95])
    : "l"(da), "l"(db), "r"(scale_d), "n"(TA), "n"(TB));
}

template<int TA, int TB>
__device__ __forceinline__ void wgmma_n48(float (&d)[24], uint64_t da, uint64_t db, int scale_d) {
  asm volatile("{\n.reg .pred p;\nsetp.ne.b32 p, %26, 0;\n"
    "wgmma.mma_async.sync.aligned.m64n48k16.f32.bf16.bf16 "
    "{%0, %1, %2, %3, %4, %5, %6, %7, %8, %9, %10, %11, %12, %13, %14, %15, %16, %17, %18, %19, %20, %21, %22, %23}, %24, %25, p, 1, 1, %27, %28;\n}\n"
    : "+f"(d[0]), "+f"(d[1]), "+f"(d[2]), "+f"(d[3]), "+f"(d[4]), "+f"(d[5]), "+f"(d[6]), "+f"(d[7]), "+f"(d[8]), "+f"(d[9]), "+f"(d[10]), "+f"(d[11]), "+f"(d[12]), "+f"(d[13]), "+f"(d[14]), "+f"(d[15]), "+f"(d[16]), "+f"(d[17]), "+f"(d[18]), "+f"(d[19]), "+f"(d[20]), "+f"(d[21]), "+f"(d[22]), "+f"(d[23])
    : "l"(da), "l"(db), "r"(scale_d), "n"(TA), "n"(TB));
}

__device__ __forceinline__ void wgmma_rs80(float (&d)[40], const uint4& a, uint64_t db, int scale_d) {
  asm volatile("{\n.reg .pred p;\nsetp.ne.b32 p, %45, 0;\n"
    "wgmma.mma_async.sync.aligned.m64n80k16.f32.bf16.bf16 {%0,%1,%2,%3,%4,%5,%6,%7,%8,%9,%10,%11,%12,%13,%14,%15,%16,%17,%18,%19,%20,%21,%22,%23,%24,%25,%26,%27,%28,%29,%30,%31,%32,%33,%34,%35,%36,%37,%38,%39}, {%40,%41,%42,%43}, %44, p, 1, 1, 1;\n}\n"
    : "+f"(d[0]), "+f"(d[1]), "+f"(d[2]), "+f"(d[3]), "+f"(d[4]), "+f"(d[5]), "+f"(d[6]), "+f"(d[7]), "+f"(d[8]), "+f"(d[9]), "+f"(d[10]), "+f"(d[11]), "+f"(d[12]), "+f"(d[13]), "+f"(d[14]), "+f"(d[15]), "+f"(d[16]), "+f"(d[17]), "+f"(d[18]), "+f"(d[19]), "+f"(d[20]), "+f"(d[21]), "+f"(d[22]), "+f"(d[23]), "+f"(d[24]), "+f"(d[25]), "+f"(d[26]), "+f"(d[27]), "+f"(d[28]), "+f"(d[29]), "+f"(d[30]), "+f"(d[31]), "+f"(d[32]), "+f"(d[33]), "+f"(d[34]), "+f"(d[35]), "+f"(d[36]), "+f"(d[37]), "+f"(d[38]), "+f"(d[39])
    : "r"(a.x), "r"(a.y), "r"(a.z), "r"(a.w), "l"(db), "r"(scale_d));
}

__device__ __forceinline__ void wgmma_ss80(float (&d)[40], uint64_t da, uint64_t db) {
  asm volatile("wgmma.mma_async.sync.aligned.m64n80k16.f32.bf16.bf16 {%0,%1,%2,%3,%4,%5,%6,%7,%8,%9,%10,%11,%12,%13,%14,%15,%16,%17,%18,%19,%20,%21,%22,%23,%24,%25,%26,%27,%28,%29,%30,%31,%32,%33,%34,%35,%36,%37,%38,%39}, %40, %41, 1, 1, 1, 0, 1;"
    : "+f"(d[0]), "+f"(d[1]), "+f"(d[2]), "+f"(d[3]), "+f"(d[4]), "+f"(d[5]), "+f"(d[6]), "+f"(d[7]), "+f"(d[8]), "+f"(d[9]), "+f"(d[10]), "+f"(d[11]), "+f"(d[12]), "+f"(d[13]), "+f"(d[14]), "+f"(d[15]), "+f"(d[16]), "+f"(d[17]), "+f"(d[18]), "+f"(d[19]), "+f"(d[20]), "+f"(d[21]), "+f"(d[22]), "+f"(d[23]), "+f"(d[24]), "+f"(d[25]), "+f"(d[26]), "+f"(d[27]), "+f"(d[28]), "+f"(d[29]), "+f"(d[30]), "+f"(d[31]), "+f"(d[32]), "+f"(d[33]), "+f"(d[34]), "+f"(d[35]), "+f"(d[36]), "+f"(d[37]), "+f"(d[38]), "+f"(d[39])
    : "l"(da), "l"(db));
}

__device__ const __align__(1024) uint32_t c_fft[11264] = {
0x2ddc2dba,0x2fe62eb5,0x2ed02eb5,0xafffaf6e,0x2e1f2dfe,0x2e3f2fbc,0x2f022ee9,0xad27af30,0x2e5e2e3f,0x1fd92b5e,0x2f302f1a,0x244ea875,0x2e992e7c,0xad96a993,0x2f5a2f46,0x2e992c32,
0xad00ad72,0xa17eac32,0xa17ea515,0xabb79cb6,0xac07ac87,0x2dfe29f1,0x1fd99648,0xafedae99,0xa9f1ab05,0x2fd42fbc,0x26a1244e,0xad96af91,0xa765a8d5,0x2aaa2e3f,0x29932875,0x2515a8d5,
0xae99adfe,0xb000aee9,0xaf6eafbc,0x2c872f30,0xaf80af1a,0xac32af02,0xae7caf02,0xaaaa217e,0xaff4afc9,0x2b5e9cb6,0xad27addc,0xaff4ae7c,0xafedb000,0x2ffc2eb5,0xab05ac5d,0xacd8af5a,
0x2c072d27,0x9fd92bb7,0xadfead00,0x2fed2e1f,0x25db2993,0xaf6eacb0,0xaf6eaed0,0x2c5d2f46,0xa5151648,0xaddcafdd,0xafffafd4,0xac321648,0xabb7a934,0x28d5a814,0xafa0afed,0xaff4af30,
0x2f302e3f,0x2fed2f1a,0x28142b5e,0x2934a875,0x30002fc9,0x26a12ddc,0xa5db1cb6,0x30002e7c,0x2f462fd4,0xaed0aa4e,0xacb0aa4e,0x29932e99,0x2d272e5e,0xae3faffc,0xaf02adfe,0xae1fa814,
0xa9f1acd8,0x26a1ab05,0x2fd42ffc,0xad96afed,0x2515a30e,0x2fff2e1f,0x2ddc2f1a,0x2c32a30e,0x2d272aaa,0x28752e7c,0x28752c32,0x2fa02f80,0x2f912e99,0xaee9a9f1,0xa8141648,0x9fd92c87,
0xafa0ae7c,0xafafaf46,0x2d002993,0xafa0ac32,0xaf91b000,0x244eac5d,0x2fbc2eb5,0xab05af5a,0xac87ae5e,0x30002dfe,0x2f6e2ffc,0x2e992814,0x1cb6a875,0x25152e1f,0x2c322e1f,0x2d722ff4,
0x27652c87,0xa9932a4e,0xaaaaadba,0xa5152c87,0xabb7a44e,0xafa0af30,0x28d59fd9,0xaff4ae5e,0xaf91ae1f,0x2814abb7,0x2ee92d00,0x1fd9ad27,0xaf5aafff,0x2fd42ed0,0x2fd42fe6,0x30002ddc,
0x2f462f6e,0x2c322fdd,0x2e7c2fdd,0xa993b000,0xab5e2934,0xafafacd8,0xad00244e,0x2f1a2dfe,0xaee9afaf,0x2f30a17e,0xadfeaff8,0xafbca30e,0x2c5da765,0xa9f12ddc,0x2d969cb6,0x2c5dacb0,
0x2bb7a993,0x2f1aa515,0x2f1a2765,0xaff4aaaa,0x2e5e2fd4,0xab052dba,0x29342f6e,0x2ee9a6a1,0xadba1fd9,0xa5dbafed,0xafddac07,0xaa4e2dfe,0xacb0aff8,0x2ddc2f02,0x9cb6ae3f,0xa765aff8,
0xaeb5af91,0xaa4eafed,0x9648ae5e,0xac5d2d4d,0x2ddca17e,0x2e7c2e3f,0x2fc92e3f,0x1cb6afa0,0x2bb72fe6,0xaff8a993,0xab5e2aaa,0x2bb72fc9,0xafbcaa4e,0x2f30a5db,0xadfeafdd,0xaee9adba,
0xacd828d5,0xaf91230e,0xaf30af02,0x2c072fa0,0xac5dafff,0x2dbaac32,0x2dbaa515,0xae99addc,0x2fc929f1,0xa9932eb5,0x2aaa2fdd,0x2fe629f1,0xa30e2dfe,0xa17eafed,0xaff8ac07,0xafaf1fd9,
0x2dfe2faf,0x28142ff8,0xae5e217e,0x2ffc230e,0xaf5aa515,0xac87af46,0xa6a1af80,0xaf5a2765,0x1cb6ae99,0x2e7c2dba,0x2fc92dba,0x2ddcac5d,0x2f1a2ee9,0xafafab05,0xad002934,0xab5e2e5e,
0x2dbaa814,0x2fdd9fd9,0x25db2f91,0x2a4eaee9,0x27652faf,0xaf4628d5,0xaf80ae1f,0xa5152faf,0xafa0addc,0x2e3fac32,0x2e3fa515,0xa17eafff,0x2dfea6a1,0xacd82dba,0x244e2f6e,0x29342fd4,
0xad27afc9,0xa30eafff,0x2faf2d72,0xad27ae7c,0x2ffc2a4e,0x28142fdd,0xae5e25db,0x2dfe2dba,0xac5d2c07,0xaa4eaf91,0x9648af30,0xaeb5acd8,0xa993aff4,0x2c322f1a,0x2e7c2f1a,0x2f462bb7,
0xae7c26a1,0xafff1648,0x2d72aa4e,0xafc926a1,0x230eaee9,0x2ff89fd9,0x217e2f91,0x2fafa814,0x2d4d2fa0,0xafed230e,0xae5eaf02,0xaf9128d5,0xb000aaaa,0x2fdda515,0x2fdd2765,0x2f6ea993,
0x9cb63000,0xacb02fd4,0xa7652fd4,0x2ddcaf5a,0x217eaffc,0x2ff4ac07,0x2875afbc,0xaff82934,0xa44e2ff4,0xadfea8d5,0xa9342fa0,0x2cd82bb7,0x25dbafe6,0x16482f46,0x29f1af80,0x25dbafc9,
0x2ff41cb6,0x2e1f2765,0x2e1f2cb0,0xa875addc,0xafbca5db,0x1fd9af5a,0xad4dad96,0xacd82fdd,0x2f5a2934,0xaeb52ee9,0x2c5d2e5e,0x3000ab05,0xaed0ab5e,0x2f80a30e,0xaaaaaf02,0xacb0ab5e,
0x25dbaffc,0x2d96afbc,0x2f5aac07,0xafdd2934,0xaaaa2fa0,0xafc92875,0xafe62875,0x29932d27,0x2d00aed0,0x28d52d72,0x2ff89cb6,0x2d00afe6,0xae5e2d96,0x2d4dafd4,0xaf91a6a1,0xafed29f1,
0xafbca17e,0xad4da875,0x1fd9aff4,0xacd82ff8,0x2e992aaa,0xaa4e2fe6,0xaa4e2fc9,0x2fd4a993,0xacb0ad96,0x2fffac87,0x2d72aeb5,0xa765ad96,0x28752f30,0xab5eac07,0xaf1a2cd8,0xae3f2f91,
0xa9342ff4,0xae5e2fa0,0xaee9a8d5,0x2b052bb7,0x2d96aed0,0x2eb59cb6,0x2c872d72,0x2d96afe6,0xaf802c5d,0x2765af6e,0xa515af6e,0xaf4625db,0x2ff8a44e,0xaff42d4d,0xa8752ffc,0xa17e2ee9,
0x2f5a244e,0x2c5d2934,0xaeb52dfe,0x3000acd8,0xacb0ad00,0x2d72aff8,0x2fffa8d5,0xa765ad00,0x217e2f80,0xaf022515,0xaf02a765,0xaf1a2f46,0x2b05afdd,0xa8142f5a,0x2c072d96,0x2d4d25db,
0x2b5eafe6,0x2f02af80,0x230e2f46,0x2b5eafc9,0xaf302d96,0xacd8a6a1,0x2c07afd4,0xaf9129f1,0x2fdda44e,0xad962ffc,0xaf5a2d4d,0xa5db2ee9,0xad72abb7,0x2e7ca17e,0x2fc9a17e,0x2fffad00,
0xaed0a5db,0xaaaaa9f1,0x2f809648,0xacb0a5db,0x28752e5e,0xaf1a2f91,0xab5ead4d,0xae3f2fed,0x2b05aff8,0x2c072875,0xa8142ff4,0x2d4d217e,0xaf6e2d72,0x2eb5afc9,0x2eb5ae7c,0x2dbaafff,
0xaf802f5a,0xafc92e99,0xafe62e99,0x2f46ad96,0x28d52b05,0xaf022fed,0x230e2cd8,0x2fa0affc,0x2fbcaf02,0xa9342d27,0x2ffcae1f,0x2c07ae3f,0xa6a1ac32,0x2a4e9cb6,0x9648ad72,0xa6a1a515,
0x28752aaa,0xa8d52cb0,0xa8d52ed0,0x2e3faf80,0x2fedaeb5,0x29349648,0x2f30aa4e,0x2814ac5d,0x1648ad4d,0x2e99acd8,0x2c87afbc,0xa9f11fd9,0xafe62d27,0x2fffafaf,0xaddc230e,0xaed02d27,
0x2fd4af30,0x2f6eae5e,0x2dbaa44e,0xa6a19fd9,0x1cb6ad27,0x2fe6aff4,0x2ed0aff4,0xad722b5e,0xafaf2cb0,0x2e1faf46,0xa8d5a993,0xafaf2ed0,0xac072f6e,0x2934ac87,0xaffc2e99,0xafbc3000,
0xa44eab5e,0x2b05ad00,0x2f91afaf,0xafbc2f1a,0xafd42d72,0x1648a765,0x1648acb0,0xafdd2fff,0xac322f5a,0xaaaa26a1,0xaf802c87,0xae7c2f5a,0x2d009fd9,0xae1f2cd8,0xad272fbc,0xabb72d4d,
0xaffc2f02,0xaee92e1f,0x244ead27,0xad4d2e3f,0xa9f12e7c,0xafdd2f80,0xaeb52aaa,0xa9f12c32,0x2d72a5db,0xafe63000,0xaed03000,0x9cb626a1,0x2fa0afbc,0xaf022f91,0x230e2b05,0x28d5a44e,
0x96482c07,0xac872d4d,0xae992b05,0x29f1a814,0x2ed0abb7,0xa9932b5e,0xaf462ff8,0x2cb0abb7,0x2f1aafff,0xa30e2765,0xa30e2cb0,0x2e1fad72,0x1fd9ac5d,0x244e9648,0x2e5eaa4e,0x2f30aeb5,
0x2ff8aed0,0x2e3faddc,0xaf022fff,0x2ff8afe6,0x2d4daf6e,0x2ee9ae99,0xa44e2c87,0x2ffcb000,0xa6a1a814,0x2f6eaf30,0x2dbaa934,0x2fd4afed,0xaf462d00,0x2fc9afa0,0x2fe6afa0,0x2f80afaf,
0x2515ac5d,0x2d72ad96,0x1cb629f1,0x2c32ac5d,0xad002814,0x2d27ad4d,0x2e1fab05,0x2bb7ac07,0xaffc2f1a,0x2cd8ad00,0x2fedafaf,0x2b05ab5e,0xadba2f80,0x2c87acb0,0x2c87aed0,0x2a4eaaaa,
0x2f802f6e,0x2fc92fdd,0x2fe62fdd,0xaf46b000,0x2fa02f91,0x2bb72e5e,0x2ff42fed,0xa8d5ad4d,0x2fbc2faf,0xa934217e,0x2ffc2ff8,0x2c07230e,0x2fd42fc9,0xaf5aad72,0x30002fff,0x2fd42e7c,
0x2bb72aaa,0x2f1a2cb0,0x2f1a2ed0,0xaff4af80,0x2cd82c5d,0x2f303000,0x2f912f5a,0xac07aeb5,0x2dba2d4d,0x25db2cd8,0x2fdd2fbc,0x2a4e9fd9,0x2e7c2e1f,0xad72a875,0x2fff2ff4,0x2fc92e1f,
0xa6a1a934,0x29f1a44e,0x2d962cd8,0xafd4adfe,0x1cb6a17e,0x2fe62e3f,0x2ed02e3f,0xad72afa0,0x28752515,0x2d272f80,0x2fa02f46,0x2875a765,0x2c072a4e,0xa93425db,0x2ffc2fdd,0x2fbc2dba,
0xae5eaf1a,0xa934ae3f,0x2b052875,0xaee9ab5e,0xac5dad72,0x2dba2765,0x2dba2cb0,0xae99afff,0xa765aa4e,0x2f802fd4,0x2f462e99,0x2515aa4e,0x230e9fd9,0x217e2cd8,0x2ff82fbc,0x2faf2d4d,
0xaffcafaf,0xaee9aff8,0x244ea17e,0xad4da30e,0xaf6eafe6,0x25dbaaaa,0x2c5d2993,0xaf6eafc9,0xad72ae99,0x2fe62dba,0x2ed02dba,0x1cb6ac5d,0xa8d5ac07,0x2bb72f30,0x2ff42f91,0x2fa02cd8,
0xadbaac07,0xafddad4d,0xa5dbab05,0xaa4e2814,0xafc9af02,0xaaaaaf1a,0x2993217e,0xafe6af02,0xafa0afff,0x2e3f2765,0x2e3f2cb0,0xa17ead72,0xad4daeb5,0x2e5e3000,0x2fed2f5a,0x2f912c5d,
0xa17e2765,0xad001cb6,0xabb7addc,0xa17e2cb0,0xad4daa4e,0xaee9afdd,0x244ea5db,0xaffcadba,0xafd4aee9,0x29f1a934,0x2d962b05,0xa6a1ae5e,0xaf46aff4,0x2fc92f1a,0x2fe62f1a,0x2f802bb7,
0x2cb02eb5,0x1cb62dba,0xaddcaf6e,0x27652eb5,0xa30e2814,0xaff8ad4d,0xa17eab05,0xafafac07,0xadfeab5e,0xa44eae3f,0x2cd82875,0xa934af1a,0xb000af80,0x2fdd2cb0,0x2fdd2ed0,0x2f6e2aaa,
0x2d723000,0x25152fd4,0x2c322fd4,0x1cb6af5a,0xae1f9fd9,0xae3faee9,0xaf02a814,0x2d272f91,0xacd8aff4,0x2ffc28d5,0xab05afa0,0xafedabb7,0x2e992515,0xad962aaa,0x2f5a2993,0x2e99a765,
0x2ff42ddc,0x2e1f2ed0,0x2e1f2fe6,0xa875afff,0xa8142c87,0xaffca9f1,0xadfe1648,0x2e5e2e99,0xaf5aaf30,0x2eb5a814,0xac5dafed,0xb000a934,0x2c32a8d5,0xa9932e3f,0x2f462875,0x2e7ca8d5,
0x2e991fd9,0x30002814,0x2f6e2ee9,0xac87af91,0x29932fa0,0xaed02875,0xacb02875,0x2f462d27,0xaff4ac32,0x2b5eaddc,0xad27afff,0xaff4a515,0x244ead96,0x1fd92fd4,0x2f3026a1,0x2e5ea9f1,
0x2814ad27,0x2dfeabb7,0x2ffc2d00,0xae5eae1f,0x2e992f80,0xaa4e2e7c,0xaa4e2c32,0x2fd42aaa,0xae7c1648,0x9cb6afdd,0xaddcafd4,0xafc91648,0xa875af91,0x2b5e2fbc,0x2f1a244e,0x2e3fab05,
0xab05aff4,0x244eafa0,0x2fbc28d5,0xaf91abb7,0x30002c32,0x26a12fff,0xa5db2ddc,0x30002515,0xaaaa2c5d,0xac32af6e,0xae7caf6e,0xaf8025db,0xad27afed,0x2e3f2dfe,0x2f021fd9,0x2e1fac07,
0xaf5aae5e,0xac5daf30,0x2eb59fd9,0xb000a44e,0x2e7ca30e,0x2ddc2e1f,0x1cb62f1a,0x2fc9a30e,0x217e2f46,0xaf02acb0,0xaf02aed0,0xaf1a2993,0xaf30ae99,0x2fbc29f1,0x2ee99648,0x2dfeac87,
0xafa0a515,0xafafa993,0x2d00aaaa,0xafa02765,0x2934ad96,0x2fed26a1,0x28142fd4,0x2f30a9f1,0x2c872fed,0xb0009fd9,0xaf6eadfe,0xae992c07,0xafffabb7,0x2fe6a17e,0x2ed0a17e,0x2ddcad00,
0xac322c87,0xaf462a4e,0x2993adba,0xae7c2c87,0xa875afed,0x2f1aab05,0x2b5e2ffc,0x2e3facd8,0x2f302e1f,0xaee92bb7,0xafbcad00,0xadfe2d27,0xaf6e9cb6,0x2eb5ac32,0x2eb5a515,0x2dbaad72,
0xaaaa2f5a,0xaed02e99,0xacb02e99,0x2f80ad96,0x2b5eaf30,0x2fafa44e,0x2d00ae5e,0xaf1a9fd9,0xac072f02,0xab05ad27,0xad4d2e1f,0x28142e3f,0x2c5daed0,0xa9f12fff,0x2d96addc,0x2c5dafe6,
0x28752f80,0xa8d52fe6,0xa8d52fc9,0x2e3faf46,0xa44eafd4,0x2f91adba,0x2b05af6e,0xafbc26a1,0x96482ffc,0xae99a44e,0xac872ee9,0x29f12d4d,0x2515aff8,0x1cb62f02,0x2d72ae3f,0x2c32aff8,
0x2eb52b05,0x2a4e2cd8,0x16482fed,0x2c5daffc,0xad72ad27,0x2cb0aff4,0x2765aff4,0xafff2b5e,0x2bb72e7c,0xaff82aaa,0xab5e2f80,0x2bb72c32,0xa814af6e,0x2b052c87,0x2d4dae99,0x2c07b000,
0x2feda8d5,0x2f30a30e,0x29342f02,0x2814afa0,0xafd49cb6,0x1648aed0,0x1648afe6,0xafdd2d72,0x2ed029f1,0xaf462eb5,0xa9932fdd,0x2cb029f1,0xad00ad4d,0x2e1f244e,0x2d27aee9,0x2bb7affc,
0x2d4daf02,0x2fbcae1f,0x2cd82d27,0x9fd9ae3f,0xaf5a2cb0,0xac87a993,0xa6a1af46,0xaf5a2ed0,0x2fffa5db,0xacb03000,0xa7653000,0x2d7226a1,0xaf1aa814,0x2fafa934,0x2d00af30,0x2b5eafed,
0x1648afbc,0x2c87affc,0x2e992934,0xa9f1ac07,0xac322faf,0xaf8028d5,0xaaaaae1f,0xae7c2faf,0x2f1aad72,0xa30e2ed0,0xa30e2fe6,0x2e1f1cb6,0xaffc26a1,0x2fedadba,0x2cd8af6e,0x2b05afd4,
0xad27ac32,0xa30ead72,0x2faf9cb6,0xad27a515,0x1fd92f6e,0xafbc2e99,0xacd8ac87,0xad4d3000,0x2c5dafbc,0x2a4e2b05,0x16482f91,0x2eb5a44e,0xaf802d00,0x2ed0afa0,0x2cb0afa0,0x2aaaafaf,
0xafe626a1,0xaddc1648,0x2fffaa4e,0xaed026a1,0x2d002c07,0xad272ffc,0xae1fa934,0xabb72fbc,0x1fd9afa0,0x2e5ea30e,0x244e2f02,0x2f30a8d5,0xadba2f46,0x2c87afe6,0x2c87afc9,0x2a4eaf80,
0xafff2d96,0xae7c2c5d,0xafc92c5d,0x2d72a9f1,0xa17e2dfe,0xaff42fbc,0xa8752ee9,0x2ff8af30,0x2fedad00,0xad4d2f1a,0x2f91ab5e,0x2e5eafaf,0x25dbae7c,0x16482993,0x29f1af46,0x25dbac32,
0xae3f2fff,0xaff82fc9,0xaff82e7c,0x2f02ad72,0x2c0725db,0xadfe2f5a,0x9fd92d96,0x2fedafdd,0x2f6eaf91,0xa6a12c07,0x2fd4acd8,0x2dbaaf30,0xa765ab5e,0x2aaaa30e,0x2993af02,0x2515ab5e,
0xa5db2dfe,0xad962ee9,0xaf5a2fbc,0x2fddaf30,0x2f46ab5e,0xa7652bb7,0x25152bb7,0x2f80aff8,0x2d00afc9,0x28d59cb6,0x2ff8addc,0x2d00ae7c,0xacd89648,0x2dfeac5d,0x2934aeb5,0x244eaa4e,
0x2c07217e,0x9fd92875,0xadfe2ff4,0x2fedaff8,0x2fddaf46,0x29f1a515,0x29f12765,0x2eb5af80,0x2515ad96,0x2ddcac87,0x2fffaeb5,0x2c32ad96,0xaf022b05,0x2fa0aee9,0x28d5ae5e,0x230ea934,
0x2f91ad00,0x2cd8ab5e,0xac072f1a,0x2f30afaf,0x2d96afc9,0x2eb5addc,0x2c879cb6,0x2d96ae7c,0xa993a6a1,0x2fc9af5a,0x2fe6af5a,0x2aaaac87,0xaff82e5e,0x2ff4affc,0x2875adfe,0x217ea814,
0x2f6eafed,0x2fd4af91,0xa6a12d4d,0x2dbaae5e,0x2515ad00,0x2fffaff8,0x2ddca8d5,0x2c32ad00,0xae1f2993,0x2fafafe6,0x2fafafc9,0x28d5aaaa,0xaf912fdd,0x2ee9af5a,0x2814ad96,0x1fd9a5db,
0x2b5eae7c,0x2f02af46,0x230e2993,0x2b5eac32,0xab059648,0x2e5eaeb5,0x2ee9ac5d,0x2934aa4e,0xafdd2e5e,0x2d96adfe,0x2f5aaffc,0x25dba814,0xaddc2faf,0x2cb0ad27,0x2765ad27,0x1cb6a30e,
0xa765a5db,0x2993a9f1,0x2aaa9648,0x2515a5db,0xaf022cd8,0x28d5a934,0x2fa0adfe,0x230ea44e,0xaf912ff8,0x2814a875,0x2ee9aff4,0x1fd9a17e,0xaa4e2ddc,0x26a1a765,0x26a1acb0,0x16489cb6,
0x2d722d96,0x25152c5d,0x2c322c5d,0x1cb6a9f1,0x2d272d4d,0xad00a814,0x2bb72c07,0x2e1f2b05,0x2cd82d00,0xaffcaf1a,0x2b052b5e,0x2fed2faf,0x2c872cb0,0xadbaaf80,0x2a4e2aaa,0x2c872ed0,
0x2e3f2ddc,0x2ff82ed0,0x2ff82fe6,0xaf02afff,0x2ee92e99,0x2d4d2f6e,0x2ffc3000,0xa44eac87,0x2f6e2f30,0xa6a12814,0x2fd42fed,0x2dba2934,0x2fc92fa0,0xaf46ad00,0x2f802faf,0x2fe62fa0,
0xac87ad4d,0x9648ac07,0x29f12814,0xae99ab05,0xa993ab5e,0x2ed02bb7,0x2cb02bb7,0xaf46aff8,0xa30ea765,0x2f1a2fff,0x2e1f2d72,0xa30eacb0,0x244e1648,0x1fd92c5d,0x2f302eb5,0x2e5e2a4e,
0xaee9ae1f,0xaffcaf02,0xad4dae3f,0x244e2d27,0xafddaf80,0xa9f1ae7c,0xa9f1ac32,0xaeb5aaaa,0xafe6b000,0x2d7225db,0x9cb6a6a1,0xaed0b000,0xaf02af91,0x2fa02fbc,0x28d5244e,0x230eab05,
0x2b052d00,0xa44e2b5e,0xafbcaf1a,0x2f912faf,0x16482765,0xafd4ad72,0xafddafff,0x16482cb0,0xaaaaa6a1,0xac32af5a,0xae7caf5a,0xaf80ac87,0xae1facd8,0x2d001fd9,0xabb7ad4d,0xad27afbc,
0x2f6e2e5e,0x2fd42f30,0xa6a11fd9,0x2dba244e,0x2fe62ff4,0x1cb62d27,0xad72ab5e,0x2ed02ff4,0x2e1f2f46,0xafafacb0,0xafafaed0,0xa8d52993,0x29342c87,0xac07af6e,0xafbcb000,0xaffcae99,
0xa8d5acb0,0x2875aaaa,0x2e3f2f80,0xa8d5aed0,0x29341648,0x2fed2eb5,0x28142c5d,0x2f302a4e,0x2e992cd8,0x16482d4d,0xa9f19fd9,0x2c872fbc,0x2fff2faf,0xafe6ad27,0xaed0ad27,0xaddca30e,
0xafc9ae99,0xaf80af5a,0x2f462d96,0xafe6ae99,0xaf02afed,0x28d5ab05,0x2fa02ffc,0x230eacd8,0xa934ad27,0x2fbc2f02,0x2c072e3f,0x2ffc2e1f,0x2a4e1cb6,0xa6a12c32,0xa6a12515,0x96482d72,
0xaaaa29f1,0xaed025db,0xacb025db,0x2f801648,0xaf1aaf91,0x2875ae5e,0xae3fafed,0xab5e2d4d,0x2c07a875,0x2b052ff8,0x2d4da17e,0xa814aff4,0x2eb52fc9,0xaf6ead72,0x2dba2fff,0x2eb52e7c,
0x2f022f80,0x2b5e2fe6,0x2b5e2fc9,0x230eaf46,0xacd826a1,0xaf30ad96,0xaf91a9f1,0x2c072fd4,0xad96affc,0x2fdd244e,0xa5dbaee9,0xaf5aad4d,0x2e7c217e,0xad722bb7,0x2fff2d00,0x2fc9217e,
0x2c5da934,0x2f5aa44e,0x30002cd8,0xaeb5adfe,0x2d722ff8,0xacb02d00,0xa7652d00,0x2fff28d5,0xaf02a515,0x217eaf80,0xaf1aaf46,0xaf022765,0xa814af5a,0x2b052fdd,0x2d4da5db,0x2c07ad96,
0xae5eafa0,0xa934aff4,0x2b05abb7,0xaee928d5,0x2eb51cb6,0x2d962ed0,0x2d962fe6,0x2c87ad72,0x27652f6e,0xaf80ac5d,0xaf46a5db,0xa5152f6e,0xaff4ad4d,0x2ff8244e,0xa17eaee9,0xa875affc,
0xad4d2875,0xafbc217e,0xacd8aff8,0x1fd92ff4,0xaa4eafe6,0x2e99aaaa,0x2fd42993,0xaa4eafc9,0x2fff2c87,0xacb02d96,0xa7652d96,0x2d722eb5,0xab5e2c07,0x2875af30,0xae3faf91,0xaf1aacd8,
0x2d962fbc,0x25db2ffc,0xafdda934,0x2f5a2c07,0xafc9a875,0xaaaaafa0,0x2993ad27,0xafe6a875,0x28d5ad72,0x2d002ed0,0x2d002fe6,0x2ff81cb6,0x2d4d2fd4,0xae5ead96,0xafeda9f1,0xaf9126a1,
0x2e1fa765,0x2ff49cb6,0xa8752ddc,0x2e1facb0,0x1fd92f5a,0xafbc25db,0xacd8afdd,0xad4d2d96,0xaeb5aee9,0x2f5aa934,0x30002b05,0x2c5dae5e,0x2f80230e,0xaed02b5e,0xacb02b5e,0xaaaa2f02,
0xacb0afd4,0x9cb6b000,0x2ddc2f5a,0xa765afd4,0x2ff42c07,0x217e2ffc,0xaff8a934,0x28752fbc,0xadfe28d5,0xa44eaff4,0x2cd8abb7,0xa934afa0,0x1648af46,0x25db2fe6,0x25db2fc9,0x29f12f80,
0xafff9648,0xae7ca6a1,0xafc9a6a1,0x2d722a4e,0x2ff81fd9,0x230e2ee9,0x2faf2814,0x217eaf91,0xafeda30e,0x2d4dafa0,0xaf91a8d5,0xae5e2f02,0x2fdd2515,0xb0002aaa,0x2f6e2993,0x2fdda765,
0xa30e2fff,0xad272fc9,0xad272e7c,0x2fafad72,0x2814afdd,0x2ffcaa4e,0x2dfeadba,0xae5ea5db,0xaa4e2f91,0xac5dac07,0xaeb52cd8,0x96482f30,0x2c32af1a,0xa9932ff4,0x2f46abb7,0x2e7caf1a,
0x2fdd1fd9,0x2dba2814,0x2a4e2ee9,0x25dbaf91,0xaf46a8d5,0x2765afaf,0xa515afaf,0xaf802e1f,0x2e3f2c32,0xafa02ddc,0xa17e2fff,0x2e3f2515,0xacd8adba,0x2dfe26a1,0x2934afd4,0x244eaf6e,
0x2814aff8,0x2dfeafaf,0x2ffca30e,0xae5ea17e,0xac872f46,0xaf5a2515,0xaf5aa765,0xa6a12f80,0x2e7cadba,0x1cb62e99,0x2ddc2c5d,0x2fc9adba,0xafaf2b05,0x2f1aaee9,0xab5eae5e,0xad00a934,
0xaf91a30e,0xacd8a8d5,0x2c07afa0,0xaf302f02,0x2dba2c32,0xac5d2fff,0xae992ddc,0x2dba2515,0xa993aeb5,0x2fc9a9f1,0x2fe6a9f1,0x2aaaafdd,0xa17e2fed,0xa30eadfe,0xafaf9fd9,0xaff82c07,
0xaa4e2fed,0xaeb52f91,0xac5dad4d,0x96482e5e,0x2e7cae3f,0x2ddc217e,0x1cb62fa0,0x2fc9ae3f,0xaff82993,0x2bb7afe6,0x2bb7afc9,0xab5eaaaa,0x2f3025db,0xafbc2a4e,0xaee92dba,0xadfe2fdd,
0x2f1a2515,0x2bb72993,0xaff42aaa,0x2f1aa765,0xab05adba,0x2e5eafd4,0x2ee926a1,0x2934af6e,0xa5db2fed,0xadba9fd9,0xaa4eadfe,0xafdd2c07,0x2ddcaf02,0xacb02ff8,0xa7652ff8,0x9cb62e3f,
0x2c32afdd,0x2f46af6e,0xa9933000,0x2e7cafdd,0xafaf2cd8,0xab5ea934,0x2f1aadfe,0xad00a44e,0x2f30217e,0xaee92faf,0xafbc230e,0xadfe2ff8,0xa9f1addc,0x2c5d2765,0x2c5d2cb0,0x2d961cb6,
0xa993aa4e,0x2765ac87,0xa515ac87,0xaaaa2dba,0xafa02f30,0xabb7244e,0xaff42e5e,0x28d51fd9,0x28142bb7,0xaf912e1f,0x1fd92d27,0x2ee9ad00,0x2fd4aed0,0xaf5a2fff,0x3000addc,0x2fd4afe6,
0xafaf2f46,0xafa02e7c,0xafa02c32,0x2d00a993,0x244e2c5d,0xaf913000,0xab052f5a,0x2fbcaeb5,0x3000adfe,0xac872e5e,0x2e99a814,0x2f6eaffc,0x2515ae1f,0x1cb62875,0x2d72aff4,0x2c32ae1f,
0x26a12b05,0xa9f12cd8,0xad962fed,0x2fd4affc,0x2fffae1f,0x2515230e,0x2c32230e,0x2ddcaf1a,0x2875ae7c,0x2d27aaaa,0x2fa0af80,0x2875ac32,0xaee929f1,0x2f91ae99,0x9fd9ac87,0xa8149648,
0x2fedaf1a,0x2f30ae3f,0x29342875,0x2814ab5e,0x26a1addc,0x3000afc9,0x3000ae7c,0xa5db9cb6,0xaed02a4e,0x2f46afd4,0x2993ae99,0xacb02a4e,0xae3f2ffc,0x2d27ae5e,0xae1f2814,0xaf022dfe,
0x9fd9abb7,0x2c07ad27,0x2fedae1f,0xadfe2d00,0xaf6e2cb0,0x25dba993,0x2c5daf46,0xaf6e2ed0,0xaddc2fdd,0xa5159648,0xac329648,0xafff2fd4,0x28d52814,0xabb72934,0xaff42f30,0xafa02fed,
0xb0002ee9,0xae992dfe,0x2c87af30,0xaf6e2fbc,0xac322f02,0xaf802f1a,0xaaaaa17e,0xae7c2f02,0x2b5e1cb6,0xaff42fc9,0xaff42e7c,0xad272ddc,0x2ffcaeb5,0xafed3000,0xacd82f5a,0xab052c5d,
0xa17e2c32,0xad002d72,0xabb71cb6,0xa17e2515,0x2dfea9f1,0xac072c87,0xafed2e99,0x1fd91648,0x2fd4afbc,0xa9f12b05,0xad962f91,0x26a1a44e,0x2aaaae3f,0xa76528d5,0x251528d5,0x2993a875,
0x2fe6aeb5,0x2ddcadba,0xafff2f6e,0x2ed0aeb5,0x2e3fafbc,0x2e1fadfe,0xad272f30,0x2f02aee9,0x1fd9ab5e,0x2e5eae3f,0x244e2875,0x2f30af1a,0xad962993,0x2e99ae7c,0x2e99ac32,0x2f5aaf46,
0x299329f1,0xa76525db,0x251525db,0x2aaa1648,0x28d52934,0xaf02acd8,0x230e244e,0x2fa02dfe,0x28142875,0xaf91aff8,0x1fd9217e,0x2ee92ff4,0x26a12765,0xaa4eaddc,0x16481cb6,0x26a12cb0,
0x2f022f46,0x2b5e2e7c,0x2b5e2c32,0x230ea993,0x2e5e2eb5,0xab051648,0x29342a4e,0x2ee92c5d,0x2d962dfe,0xafddae5e,0x25db2814,0x2f5a2ffc,0x2cb02d27,0xaddcafaf,0x1cb6230e,0x27652d27,
0x2fd42f91,0x2f6e2fed,0x2dba2e5e,0xa6a1ad4d,0x2fff2ff8,0x25152d00,0x2c322d00,0x2ddc28d5,0x2faf2fe6,0xae1fa993,0x28d52aaa,0x2faf2fc9,0x2ee92f5a,0xaf91afdd,0x1fd925db,0x28142d96,
0x2cd82b5e,0x2f912d00,0x2f302faf,0xac07af1a,0x2eb52ddc,0x2d962fc9,0x2d962e7c,0x2c871cb6,0x2fc92f5a,0xa99326a1,0x2aaa2c87,0x2fe62f5a,0x2ff42ffc,0xaff8ae5e,0x217e2814,0x28752dfe,
0x9fd9a875,0x2c07a17e,0x2fed2ff8,0xadfeaff4,0x29f12515,0x2fdd2f46,0x2eb52f80,0x29f1a765,0x2ddc2c87,0x25152d96,0x2c322d96,0x2fff2eb5,0x2fa02ee9,0xaf02ab05,0x230e2934,0x28d52e5e,
0xad96aee9,0xa5dbadfe,0x2fdd2f30,0xaf5aafbc,0xa765abb7,0x2f462b5e,0x2f802ff8,0x2515abb7,0x28d51cb6,0x2d002fc9,0x2d002e7c,0x2ff82ddc,0x2dfe2c5d,0xacd81648,0x244e2a4e,0x29342eb5,
0xaff8afc9,0xae3fafff,0x2f022d72,0xaff8ae7c,0xadfeaf5a,0x2c07a5db,0x2fed2fdd,0x9fd9ad96,0xa6a1ac07,0x2f6e2f91,0x2dba2f30,0x2fd42cd8,0x2aaa230e,0xa7652b5e,0x25152b5e,0x29932f02,
0xae7cac5d,0xafffad96,0x2d7229f1,0xafc9ac5d,0xaff4afbc,0xa17eadfe,0x2ff82f30,0xa875aee9,0xad4daf1a,0x2fed2d00,0x2e5e2faf,0x2f912b5e,0x1648a993,0x25db2e7c,0x25db2c32,0x29f12f46,
0xaddc9648,0xafe6a6a1,0xaed0a6a1,0x2fff2a4e,0xad27affc,0x2d00ac07,0xabb7afbc,0xae1f2934,0x2e5e230e,0x1fd92fa0,0x2f3028d5,0x244eaf02,0x2c872fe6,0xadbaaf46,0x2a4e2f80,0x2c872fc9,
0xa30e2d72,0xad272c32,0xad272515,0x2faf1cb6,0xafbcae99,0x1fd9af6e,0xad4db000,0xacd82c87,0x2a4eab05,0x2c5d2fbc,0x2eb5244e,0x1648af91,0x2ed02fa0,0xaf80ad00,0x2aaa2faf,0x2cb02fa0,
0x2c872ffc,0x16482fbc,0xa9f12c07,0x2e99a934,0xaf80a8d5,0xac32afaf,0xae7cafaf,0xaaaa2e1f,0xa30eaed0,0x2f1a2d72,0x2e1f9cb6,0xa30eafe6,0x2fed2dba,0xaffca6a1,0x2b052fd4,0x2cd82f6e,
0x2fbc2e1f,0x2d4d2f02,0x9fd92e3f,0x2cd8ad27,0xac872993,0xaf5aacb0,0xaf5aaed0,0xa6a12f46,0xacb0b000,0x2fff25db,0x2d72a6a1,0xa765b000,0x2faf2934,0xaf1a2814,0x2b5e2fed,0x2d002f30,
0x2f30230e,0x2fed28d5,0x28142fa0,0x2934af02,0x16482ed0,0xafd41cb6,0xafddad72,0x16482fe6,0xaf46aeb5,0x2ed0a9f1,0x2cb0a9f1,0xa993afdd,0x2e1fa44e,0xad002d4d,0x2bb72ffc,0x2d272ee9,
0x2a4eacd8,0x2eb5ab05,0x2c5d2ffc,0x1648afed,0x2cb02ff4,0xad722d27,0xafffab5e,0x27652ff4,0xaff8aaaa,0x2bb7ae7c,0x2bb7ac32,0xab5eaf80,0x2b05ac87,0xa8142f6e,0x2c073000,0x2d4d2e99,
0xa8d5afe6,0x2875af80,0x2e3f2f46,0xa8d5afc9,0x2f912dba,0xa44e2fd4,0xafbca6a1,0x2b052f6e,0xae99244e,0x9648affc,0x29f1ad4d,0xac87aee9,0x1cb6af02,0x25152ff8,0x2c322ff8,0x2d722e3f,
0xaed0ae99,0xaaaaaf5a,0x2f802d96,0xacb0ae99,0x2faf244e,0x2b5e2f30,0xaf1a1fd9,0x2d002e5e,0xab052d27,0xac07af02,0x2814ae3f,0xad4dae1f,0xa9f1afff,0x2c5d2ed0,0x2c5d2fe6,0x2d962ddc,
0xaf46aa4e,0xac32ac87,0xae7cac87,0x29932dba,0x2f1a2b05,0xa8752fed,0x2e3f2cd8,0x2b5eaffc,0xaee9abb7,0x2f30ae1f,0xadfead27,0xafbc2d00,0x2eb52c32,0xaf6e1cb6,0x2dba2d72,0x2eb52515,
0xafaf2993,0xafa02515,0xafa0a765,0x2d002aaa,0x2feda6a1,0x29342d96,0x2f3029f1,0x2814afd4,0xb0001fd9,0x2c87afed,0xae99ac07,0xaf6e2dfe,0x2fe6217e,0xafff2bb7,0x2ddc2d00,0x2ed0217e,
0xac5d2f30,0xaf5a2e5e,0xb000244e,0x2eb51fd9,0x2ddcae1f,0x2e7c230e,0x2fc9230e,0x1cb6af1a,0xaf022cb0,0x217eaf46,0xaf1aa993,0xaf022ed0,0x2fbca9f1,0xaf302e99,0x2dfe2c87,0x2ee91648,
0x244e2fa0,0xab052ff4,0xaf912bb7,0x2fbca8d5,0x26a1afff,0x3000ac32,0x3000a515,0xa5dbaddc,0xac322f6e,0xaaaaac5d,0xaf80a5db,0xae7c2f6e,0x2e3fadfe,0xad272fed,0x2e1f2c07,0x2f029fd9,
0x2dfe2bb7,0x28142d27,0xae5e2e1f,0x2ffcad00,0xaa4eae7c,0x2e99af80,0x2fd4aaaa,0xaa4eac32,0x9cb62fdd,0xae7c9648,0xafc99648,0xaddc2fd4,0x2b5eafbc,0xa8752f91,0x2e3f2b05,0x2f1aa44e,
0x3000a814,0x2e999fd9,0xac872f91,0x2f6eaee9,0xaed0a875,0x2993afa0,0x2f46ad27,0xacb0a875,0x2b5e2ddc,0xaff42c32,0xaff42515,0xad272fff,0x1fd9afd4,0x244e2d96,0x2e5e29f1,0x2f30a6a1,
0x2e1faed0,0x2ff4addc,0xa8752fff,0x2e1fafe6,0xaffc29f1,0xa814ac87,0x2e5eae99,0xadfe9648,0x2eb52814,0xaf5a2f30,0xb0002934,0xac5d2fed,0xa993ae3f,0x2c3228d5,0x2e7c28d5,0x2f46a875,
0x2515afd4,0x2d72b000,0x1cb62f5a,0x2c32afd4,0xae3f2ee9,0xae1f1fd9,0x2d27af91,0xaf022814,0x2ffca8d5,0xacd82ff4,0xafed2bb7,0xab052fa0,0xad96aaaa,0x2e99a515,0x2e992765,0x2f5aa993,
0x1cb6adba,0x2cb0aeb5,0x2765aeb5,0xaddc2f6e,0xaff82d4d,0xa30ea814,0xafaf2c07,0xa17e2b05,0xa44e2e3f,0xadfe2b5e,0xa9342f1a,0x2cd8a875,0x2fddacb0,0xb0002f80,0x2f6eaaaa,0x2fddaed0,
0xad009cb6,0xa17ea765,0xa17eacb0,0xabb72ddc,0xaee92fdd,0xad4d2a4e,0xaffc2dba,0x244e25db,0x29f12934,0xafd42ee9,0xa6a12e5e,0x2d96ab05,0x2fc9af1a,0xaf462ff4,0x2f80abb7,0x2fe6af1a,
0xafdd2d4d,0xadba2c07,0xaa4ea814,0xa5db2b05,0xaaaa2f1a,0xafc92f02,0xafe62f02,0x2993a17e,0x2e3fa765,0xafa02fff,0xa17e2d72,0x2e3facb0,0x2e5eb000,0xad4d2eb5,0x2f91ac5d,0x2fedaf5a,
0xaee92ff8,0xaffc2faf,0xad4d230e,0x244e217e,0x25db2aaa,0xaf6e2fe6,0xaf6e2fc9,0x2c5da993,0x2fe6adba,0xad722e99,0x1cb62c5d,0x2ed0adba,0x2bb7af30,0xa8d52c07,0x2fa0acd8,0x2ff4af91,
0xa9342e3f,0xae5e2f1a,0xaee92b5e,0x2b05a875,0x2dbaa765,0xac5d2d72,0xae992fff,0x2dbaacb0,0x2f80afd4,0xa7652a4e,0x25152a4e,0x2f46ae99,0x217eacd8,0x230e1fd9,0x2fafad4d,0x2ff8afbc,
0x29f1244e,0xa6a12934,0xafd42dfe,0x2d96acd8,0x2fe6ae3f,0x1cb6217e,0xad722fa0,0x2ed0ae3f,0x2d27af80,0x2875a515,0x28752765,0x2fa0af46,0xa934a5db,0x2c07aa4e,0x2fbcadba,0x2ffcafdd,
0x2f1aacb0,0x2bb7aaaa,0xaff42f80,0x2f1aaed0,0x2f30b000,0x2cd8ac5d,0xac072eb5,0x2f91af5a,0x25dbacd8,0x2dbaad4d,0x2a4e1fd9,0x2fddafbc,0xad722875,0x2e7cae1f,0x2fc9ae1f,0x2fffaff4,
0x2fc9afdd,0x2f80af6e,0xaf463000,0x2fe6afdd,0x2bb7ae5e,0x2fa0af91,0xa8d52d4d,0x2ff4afed,0xa934a17e,0x2fbcafaf,0x2c07a30e,0x2ffcaff8,0xaf5a2d72,0x2fd4afc9,0x2fd4ae7c,0x3000afff,
0x9d4d9e16,0xada6ae7d,0x9b769c84,0xabf0accf,0x985299e4,0xa897aa43,0x90b6957f,0xa102a5d8,0x13db0a48,0x242c1aad,0x191b1712,0x296d2783,0x1c201aad,0x2c632b1a,0x1db21ce9,0x2e112d3a,
0xa3f4a491,0xae51af42,0xa199a2c6,0xac70ad60,0x9e7ba06b,0xa922ab00,0x97129c20,0xa199a688,0x19e410b6,0x24aa1b76,0x1fa81d4d,0x2a112833,0x222f2102,0x2ce82bf0,0x2445235d,0x2ec92dd8,
0xa6a1a79c,0xaefcb004,0xa4aaa5a5,0xace8adf2,0xa166a35d,0xa9acabbe,0x99e49edf,0xa22fa738,0x1ce913db,0x25281c20,0x2262206b,0x2ab528a4,0x2528242c,0x2d6d2c63,0x271f2623,0x2f822e77,
0xa8a4a954,0xafa8b067,0xa688a7e8,0xad60ae84,0xa38fa528,0xaa37ac3d,0x9c20a0d0,0xa2c6a7e8,0x1edf157f,0x25a51c84,0x2478222f,0x2b592915,0x273825d8,0x2df22ccf,0x28fc284c,0x301d2f16,
0xa9f8aadb,0xb02ab0ca,0xa833a915,0xadd8af16,0xa4dca6a1,0xaac1ac9c,0x9d4da22f,0xa35da84c,0x206b1712,0x26231ce9,0x25bf23f4,0x2bfd2987,0x28a42783,0x2e772d3a,0x2a692987,0x307a2fb5,
0xab4cac31,0xb081b12e,0xa922aa37,0xae51afa8,0xa5f1a80d,0xab4cacfb,0x9e7ba38f,0xa3f4a8a4,0x21661852,0x26a11d4d,0x270524dc,0x2c5029f8,0x29ac2897,0x2efc2da6,0x2bd72ac1,0x30d7302a,
0xac50acf5,0xb0d7b192,0xaa11ab59,0xaec9b01d,0xa705a8ca,0xabd7ad5a,0x9fa8a478,0xa445a8fc,0x2262191b,0x271f1db2,0x282625bf,0x2ca22a69,0x2ab5296d,0x2f822e11,0x2ca22bfd,0x3135307a,
0xacfbadb9,0xb12eb1f7,0xab00ac3d,0xaf42b067,0xa80da987,0xac31adb9,0xa06ba528,0xa491a954,0x235d19e4,0x279c1e16,0x28ca26a1,0x2cf52adb,0x2bbe2a43,0x30042e7d,0x2d5a2c9c,0x319230ca,
0xb185b25c,0xb426b4cc,0xafbbb0b1,0xb1c6b306,0xac76ae18,0xaea3b08a,0xa4dca9ac,0xa738ac37,0x280d1e7b,0x2a0520d0,0x2d472b4c,0x2fdb2d6d,0x30472ee9,0x32663128,0x31f0311b,0x347933a8,
0xb1ddb2c1,0xb453b501,0xb01ab0fb,0xb204b352,0xacbcae77,0xaee9b0ba,0xa528aa05,0xa783ac63,0x284c1edf,0x2a432102,0x2d992bbe,0x30172da6,0x308a2f55,0x32aa315f,0x324f316b,0x34aa33fc,
0xb235b327,0xb481b537,0xb057b145,0xb242b39e,0xad01aed6,0xaf2fb0eb,0xa573aa5d,0xa7cfac90,0x288b1f44,0x2a822134,0x2deb2c18,0x30412ddf,0x30ce2fc2,0x32ef3196,0x32ae31bc,0x34db3428,
0xb28db38e,0xb4afb56d,0xb094b18f,0xb280b3eb,0xad47af36,0xaf75b11b,0xa5bfaab5,0xa80dacbc,0x28ca1fa8,0x2ac12166,0x2e3e2c50,0x306a2e18,0x31113017,0x333531cd,0x330d320e,0x350d3452,
0xb2e5b3f5,0xb4ddb5a3,0xb0d1b1da,0xb2beb41c,0xad8caf95,0xafbbb14b,0xa60aab0d,0xa833ace8,0x29092006,0x2b002199,0x2e902c89,0x30942e51,0x3155304d,0x337a3204,0x336d325f,0x3540347c,
0xb33eb42e,0xb50cb5da,0xb10eb224,0xb2fcb443,0xadd2aff5,0xb001b17c,0xa655ab65,0xa859ad14,0x29482039,0x2b4021cb,0x2ee32cc2,0x30be2e8a,0x31993084,0x33c0323b,0x33cd32b1,0x357234a6,
0xb398b463,0xb53ab612,0xb14bb26f,0xb33bb469,0xae18b02a,0xb024b1ac,0xa6a1abbe,0xa87ead40,0x2987206b,0x2b7f21fd,0x2f362cfb,0x30e72ec3,0x31dd30ba,0x34033273,0x34173303,0x35a534d1,
0xb3f2b497,0xb569b64a,0xb189b2bb,0xb37ab490,0xae5eb05a,0xb047b1dd,0xa6ecac0b,0xa8a4ad6d,0x29c6209d,0x2bbe222f,0x2f882d34,0x31112efc,0x322130f1,0x342632aa,0x34483356,0x35d934fc,
0xb599b682,0xb722b82e,0xb3b9b4b7,0xb4ddb5f9,0xb06ab20e,0xb185b398,0xa8caad99,0xa9f8aefc,0x2bfd2262,0x2cfb23f4,0x313b2f36,0x328d3081,0x344932e2,0x35693453,0x360d3527,0x37bd368b,
0xb5c9b6bb,0xb755b84d,0xb3f8b4df,0xb4feb622,0xb08db23e,0xb1a9b3ca,0xa8f0adc5,0xaa1eaf29,0x2c1e2294,0x2d1b2413,0x31652f6f,0x32b7309d,0x346d331a,0x358e3470,0x36413553,0x37f536ba,
0xb5f9b6f5,0xb789b86d,0xb41cb506,0xb51fb64c,0xb0b1b26f,0xb1cdb3fc,0xa915adf2,0xaa43af55,0x2c3d22c6,0x2d3a242c,0x318f2fa8,0x32e230ba,0x34903352,0x35b3348d,0x3676357e,0x381736e8,
0xb629b72f,0xb7bdb88d,0xb43cb52e,0xb540b676,0xb0d4b2a1,0xb1f0b417,0xa93bae1e,0xaa69af82,0x2c5d22f9,0x2d5a2445,0x31b92fe2,0x330d30d7,0x34b4338b,0x35d934aa,0x36ab35ab,0x38343717,
0xb65ab76a,0xb7f1b8ad,0xb45cb556,0xb561b6a0,0xb0f7b2d2,0xb214b430,0xa961ae4b,0xaa8fafaf,0x2c7d232b,0x2d79245f,0x31e3300e,0x333830f4,0x34d833c3,0x35fe34c7,0x36e035d7,0x38513746,
0xb68bb7a5,0xb813b8ce,0xb47cb57e,0xb582b6ca,0xb11bb303,0xb238b449,0xa987ae77,0xaab5afdb,0x2c9c235d,0x2d992478,0x320e302a,0x33633111,0x34fc33fc,0x362434e4,0x37173604,0x386f3775,
0xb6bdb7e2,0xb82eb8f0,0xb49cb5a7,0xb5a3b6f5,0xb13eb335,0xb25cb463,0xa9acaea3,0xaadbb004,0x2cbc238f,0x2db92491,0x32383047,0x338e312e,0x3520341a,0x364a3501,0x374d3631,0x388d37a5,
0xb6efb80f,0xb849b911,0xb4bdb5d0,0xb5c5b720,0xb162b366,0xb280b47c,0xa9d2aed0,0xab00b01a,0x2cdb23c2,0x2dd824aa,0x32623064,0x33b9314b,0x35453437,0x3670351f,0x3785365e,0x38ab37d6,
0xb865b934,0xb94dba5c,0xb5e7b74c,0xb6fcb85a,0xb2a4b495,0xb3c6b564,0xab26b031,0xac2bb0e4,0x2df824c3,0x2ef6258c,0x33e43168,0x34a13252,0x3697353c,0x37d4362d,0x38ca3803,0x39d038d0,
0xb880b957,0xb96bba84,0xb609b777,0xb720b872,0xb2c8b4af,0xb3ebb57e,0xab4cb047,0xac3db0fb,0x2e1824dc,0x2f1625a5,0x34083185,0x34b7326f,0x36bd355a,0x37fd364c,0x38e9381c,0x39f338eb,
0xb89cb97a,0xb98abaad,0xb62bb7a4,0xb744b88a,0xb2ecb4c9,0xb408b599,0xab72b05d,0xac50b111,0x2e3724f5,0x2f3625bf,0x341e31a2,0x34ce328d,0x36e43577,0x3813366b,0x39093835,0x3a173906,
0xb8b9b99e,0xb9aabad7,0xb64db7d0,0xb768b8a2,0xb310b4e2,0xb41ab5b3,0xab98b074,0xac63b128,0x2e57250f,0x2f5525d8,0x343331c0,0x34e432aa,0x370b3595,0x3828368a,0x3929384e,0x3a3b3922,
0xb8d6b9c3,0xb9cabb02,0xb670b7fd,0xb78cb8ba,0xb335b4fc,0xb42db5ce,0xabbeb08a,0xac76b13e,0x2e772528,0x2f7525f1,0x344931dd,0x34fa32c8,0x373335b3,0x383d36a9,0x39493868,0x3a60393e,
0xb8f3b9e8,0xb9ebbb2d,0xb693b815,0xb7b1b8d2,0xb359b516,0xb43fb5e9,0xabe3b0a1,0xac89b155,0x2e972541,0x2f95260a,0x345f31fa,0x351132e5,0x375b35d2,0x385236c8,0x396a3881,0x3a86395a,
0xb910ba0e,0xba0cbb59,0xb6b6b82c,0xb7d6b8eb,0xb37db530,0xb452b604,0xac05b0b7,0xac9cb16b,0x2eb6255a,0x2fb52623,0x34753217,0x35273303,0x378335f0,0x386836e8,0x398c389b,0x3aac3977,
0xb92eba35,0xba2dbb87,0xb6d9b843,0xb7fbb904,0xb3a2b54a,0xb464b61e,0xac18b0ce,0xacafb182,0x2ed62573,0x2fd5263c,0x348b3235,0x353e3321,0x37ab360e,0x387d3708,0x39ae38b6,0x3ad33994,
0x9ce99db2,0xad3aae11,0x9aad9c20,0xab1aac63,0x9712991b,0xa783a96d,0x8a4893db,0x9aada42c,0x157f10b6,0x25d82102,0x19e41852,0x2a432897,0x1c841b76,0x2ccf2bf0,0x1e161d4d,0x2e7d2da6,
0xa35da445,0xadd8aec9,0xa102a22f,0xabf0ace8,0x9d4d9fa8,0xa833aa11,0x90b699e4,0x9b76a4aa,0x1c201712,0x26882199,0x206b1e7b,0x2b002922,0x22c62199,0x2d602c70,0x249123f4,0x2f422e51,
0xa623a71f,0xae77af82,0xa42ca528,0xac63ad6d,0xa06ba262,0xa8a4aab5,0x93db9ce9,0x9c20a528,0x1edf19e4,0x2738222f,0x235d2166,0x2bbe29ac,0x25a524aa,0x2df22ce8,0x279c26a1,0x30042efc,
0xa84ca8fc,0xaf16b01d,0xa5d8a738,0xaccfadf2,0xa22fa478,0xa915ab59,0x957f9edf,0x9c84a5a5,0x20d01c20,0x27e822c6,0x2528238f,0x2c3d2a37,0x27e82688,0x2e842d60,0x295428a4,0x30672fa8,
0xa987aa69,0xafb5b07a,0xa783a8a4,0xad3aae77,0xa3f4a5bf,0xa987abfd,0x9712a06b,0x9ce9a623,0x222f1d4d,0x284c235d,0x26a124dc,0x2c9c2ac1,0x29152833,0x2f162dd8,0x2adb29f8,0x30ca302a,
0xaac1abd7,0xb02ab0d7,0xa897a9ac,0xada6aefc,0xa4dca705,0xa9f8ac50,0x9852a166,0x9d4da6a1,0x238f1e7b,0x28a423f4,0x280d25f1,0x2cfb2b4c,0x2a372922,0x2fa82e51,0x2c312b4c,0x312e3081,
0xabfdaca2,0xb07ab135,0xa96daab5,0xae11af82,0xa5bfa826,0xaa69aca2,0x991ba262,0x9db2a71f,0x24781fa8,0x28fc2445,0x28ca2705,0x2d5a2bd7,0x2b592a11,0x301d2ec9,0x2cf52c50,0x319230d7,
0xac9cad5a,0xb0cab192,0xaa43abbe,0xae7db004,0xa6a1a8ca,0xaadbacf5,0x99e4a35d,0x9e16a79c,0x2528206b,0x29542491,0x2987280d,0x2db92c31,0x2c3d2b00,0x30672f42,0x2db92cfb,0x31f7312e,
0xb11bb1f0,0xb3a8b479,0xaee9b047,0xb128b266,0xab4cad47,0xad6dafdb,0x9e7ba80d,0xa0d0aa05,0x29ac24dc,0x2c372738,0x2e182c76,0x308a2ea3,0x30b12fbb,0x330631c6,0x325c3185,0x34cc3426,
0xb16bb24f,0xb3fcb4aa,0xaf55b08a,0xb15fb2aa,0xabbead99,0xada6b017,0x9edfa84c,0xa102aa43,0x2a052528,0x2c632783,0x2e772cbc,0x30ba2ee9,0x30fb301a,0x33523204,0x32c131dd,0x35013453,
0xb1bcb2ae,0xb428b4db,0xafc2b0ce,0xb196b2ef,0xac18adeb,0xaddfb041,0x9f44a88b,0xa134aa82,0x2a5d2573,0x2c9027cf,0x2ed62d01,0x30eb2f2f,0x31453057,0x339e3242,0x33273235,0x35373481,
0xb20eb30d,0xb452b50d,0xb017b111,0xb1cdb335,0xac50ae3e,0xae18b06a,0x9fa8a8ca,0xa166aac1,0x2ab525bf,0x2cbc280d,0x2f362d47,0x311b2f75,0x318f3094,0x33eb3280,0x338e328d,0x356d34af,
0xb25fb36d,0xb47cb540,0xb04db155,0xb204b37a,0xac89ae90,0xae51b094,0xa006a909,0xa199ab00,0x2b0d260a,0x2ce82833,0x2f952d8c,0x314b2fbb,0x31da30d1,0x341c32be,0x33f532e5,0x35a334dd,
0xb2b1b3cd,0xb4a6b572,0xb084b199,0xb23bb3c0,0xacc2aee3,0xae8ab0be,0xa039a948,0xa1cbab40,0x2b652655,0x2d142859,0x2ff52dd2,0x317c3001,0x3224310e,0x344332fc,0x342e333e,0x35da350c,
0xb303b417,0xb4d1b5a5,0xb0bab1dd,0xb273b403,0xacfbaf36,0xaec3b0e7,0xa06ba987,0xa1fdab7f,0x2bbe26a1,0x2d40287e,0x302a2e18,0x31ac3024,0x326f314b,0x3469333b,0x34633398,0x3612353a,
0xb356b448,0xb4fcb5d9,0xb0f1b221,0xb2aab426,0xad34af88,0xaefcb111,0xa09da9c6,0xa22fabbe,0x2c0b26ec,0x2d6d28a4,0x305a2e5e,0x31dd3047,0x32bb3189,0x3490337a,0x349733f2,0x364a3569,
0xb527b60d,0xb68bb7bd,0xb2e2b449,0xb453b569,0xaf36b13b,0xb081b28d,0xa262abfd,0xa3f4acfb,0x2d9928ca,0x2efc29f8,0x320e306a,0x33983185,0x34b733b9,0x35f934dd,0x36823599,0x382e3722,
0xb553b641,0xb6bab7f5,0xb31ab46d,0xb470b58e,0xaf6fb165,0xb09db2b7,0xa294ac1e,0xa413ad1b,0x2dc528f0,0x2f292a1e,0x323e308d,0x33ca31a9,0x34df33f8,0x362234fe,0x36bb35c9,0x384d3755,
0xb57eb676,0xb6e8b817,0xb352b490,0xb48db5b3,0xafa8b18f,0xb0bab2e2,0xa2c6ac3d,0xa42cad3a,0x2df22915,0x2f552a43,0x326f30b1,0x33fc31cd,0x3506341c,0x364c351f,0x36f535f9,0x386d3789,
0xb5abb6ab,0xb717b834,0xb38bb4b4,0xb4aab5d9,0xafe2b1b9,0xb0d7b30d,0xa2f9ac5d,0xa445ad5a,0x2e1e293b,0x2f822a69,0x32a130d4,0x341731f0,0x352e343c,0x36763540,0x372f3629,0x388d37bd,
0xb5d7b6e0,0xb746b851,0xb3c3b4d8,0xb4c7b5fe,0xb00eb1e3,0xb0f4b338,0xa32bac7d,0xa45fad79,0x2e4b2961,0x2faf2a8f,0x32d230f7,0x34303214,0x3556345c,0x36a03561,0x376a365a,0x38ad37f1,
0xb604b717,0xb775b86f,0xb3fcb4fc,0xb4e4b624,0xb02ab20e,0xb111b363,0xa35dac9c,0xa478ad99,0x2e772987,0x2fdb2ab5,0x3303311b,0x34493238,0x357e347c,0x36ca3582,0x37a5368b,0x38ce3813,
0xb631b74d,0xb7a5b88d,0xb41ab520,0xb501b64a,0xb047b238,0xb12eb38e,0xa38facbc,0xa491adb9,0x2ea329ac,0x30042adb,0x3335313e,0x3463325c,0x35a7349c,0x36f535a3,0x37e236bd,0x38f0382e,
0xb65eb785,0xb7d6b8ab,0xb437b545,0xb51fb670,0xb064b262,0xb14bb3b9,0xa3c2acdb,0xa4aaadd8,0x2ed029d2,0x301a2b00,0x33663162,0x347c3280,0x35d034bd,0x372035c5,0x380f36ef,0x39113849,
0xb803b8ca,0xb8d0b9d0,0xb53cb697,0xb62db7d4,0xb168b3e4,0xb252b4a1,0xa4c3adf8,0xa58caef6,0x30312b26,0x30e42c2b,0x349532a4,0x356433c6,0x374c35e7,0x385a36fc,0x39343865,0x3a5c394d,
0xb81cb8e9,0xb8ebb9f3,0xb55ab6bd,0xb64cb7fd,0xb185b408,0xb26fb4b7,0xa4dcae18,0xa5a5af16,0x30472b4c,0x30fb2c3d,0x34af32c8,0x357e33eb,0x37773609,0x38723720,0x39573880,0x3a84396b,
0xb835b909,0xb906ba17,0xb577b6e4,0xb66bb813,0xb1a2b41e,0xb28db4ce,0xa4f5ae37,0xa5bfaf36,0x305d2b72,0x31112c50,0x34c932ec,0x35993408,0x37a4362b,0x388a3744,0x397a389c,0x3aad398a,
0xb84eb929,0xb922ba3b,0xb595b70b,0xb68ab828,0xb1c0b433,0xb2aab4e4,0xa50fae57,0xa5d8af55,0x30742b98,0x31282c63,0x34e23310,0x35b3341a,0x37d0364d,0x38a23768,0x399e38b9,0x3ad739aa,
0xb868b949,0xb93eba60,0xb5b3b733,0xb6a9b83d,0xb1ddb449,0xb2c8b4fa,0xa528ae77,0xa5f1af75,0x308a2bbe,0x313e2c76,0x34fc3335,0x35ce342d,0x37fd3670,0x38ba378c,0x39c338d6,0x3b0239ca,
0xb881b96a,0xb95aba86,0xb5d2b75b,0xb6c8b852,0xb1fab45f,0xb2e5b511,0xa541ae97,0xa60aaf95,0x30a12be3,0x31552c89,0x35163359,0x35e9343f,0x38153693,0x38d237b1,0x39e838f3,0x3b2d39eb,
0xb89bb98c,0xb977baac,0xb5f0b783,0xb6e8b868,0xb217b475,0xb303b527,0xa55aaeb6,0xa623afb5,0x30b72c05,0x316b2c9c,0x3530337d,0x36043452,0x382c36b6,0x38eb37d6,0x3a0e3910,0x3b593a0c,
0xb8b6b9ae,0xb994bad3,0xb60eb7ab,0xb708b87d,0xb235b48b,0xb321b53e,0xa573aed6,0xa63cafd5,0x30ce2c18,0x31822caf,0x354a33a2,0x361e3464,0x384336d9,0x390437fb,0x3a35392e,0x3b873a2d,
0x214d2216,0x319b326c,0x1f762084,0x2fe830c8,0x1c521de4,0x2c962e40,0x14b6197f,0x250229d7,0x97db8e48,0xa82c9ead,0x9d1b9b12,0xad6bab82,0xa0209ead,0xb05eaf14,0xa1b2a0e9,0xb204b131,
0x27f32890,0x3241332b,0x259826c6,0x306a3156,0x227b246b,0x2d202efb,0x1b122020,0x25982a87,0x9de494b6,0xa8aa9f76,0xa3a8a14d,0xae0eac32,0xa62fa502,0xb0e1afe8,0xa845a75d,0xb2b6b1cc,
0x2aa02b9b,0x32e733e8,0x28aa29a5,0x30e131e5,0x2566275d,0x2daa2fb6,0x1de422df,0x262f2b36,0xa0e997db,0xa927a020,0xa661a46b,0xaeb0aca2,0xa927a82c,0xb163b05e,0xab1daa22,0xb368b266,
0x2ca22d52,0x338d3452,0x2a872be6,0x31563273,0x278f2927,0x2e333039,0x202024cf,0x26c62be6,0xa2df997f,0xa9a5a084,0xa877a62f,0xaf53ad13,0xab36a9d7,0xb1e5b0c8,0xacfaac4b,0xb40cb300,
0x2df52ed6,0x341834b0,0x2c322d13,0x31cc3300,0x28dc2aa0,0x2ebd3096,0x214d262f,0x275d2c4b,0xa46b9b12,0xaa22a0e9,0xa9bea7f3,0xaff5ad84,0xaca2ab82,0xb266b131,0xae65ad84,0xb464b399,
0x2f46302c,0x346a350c,0x2d202e33,0x3241338d,0x29f02c0c,0x2f4630f3,0x227b278f,0x27f32ca2,0xa5669c52,0xaaa0a14d,0xab04a8dc,0xb04badf5,0xadaaac96,0xb2e7b19b,0xafcfaebd,0xb4bcb418,
0x304b30ed,0x34bc3568,0x2e0e2f53,0x32b6340c,0x2b042cc8,0x2fcf3150,0x23a82877,0x28452cfa,0xa6619d1b,0xab1da1b2,0xac25a9be,0xb09cae65,0xaeb0ad6b,0xb368b204,0xb09caff5,0xb512b464,
0x30f331ad,0x350c35c4,0x2efb3039,0x332b3452,0x2c0c2d84,0x302c31ad,0x246b2927,0x28902d52,0xa75d9de4,0xab9ba216,0xacc8aaa0,0xb0edaed6,0xafb6ae40,0xb3e8b26c,0xb150b096,0xb568b4b0,
0x355d361e,0x37c63867,0x339f3497,0x359836b4,0x3071320a,0x32913473,0x28dc2daa,0x2b363032,0xac0ca27b,0xae01a4cf,0xb13eaf46,0xb3bdb163,0xb434b2d5,0xb627b506,0xb5beb4fa,0xb826b73e,
0x35ac3678,0x3808388f,0x340934dd,0x35cf36f5,0x30b53266,0x32d534a0,0x29272e01,0x2b82305e,0xac4ba2df,0xae40a502,0xb18eafb6,0xb406b19b,0xb473b33d,0xb663b539,0xb612b545,0xb84cb784,
0x35fb36d0,0x382c38b7,0x34433521,0x36073736,0x30f932c2,0x331834ce,0x29722e59,0x2bcd308a,0xac89a344,0xae7ea534,0xb1dfb013,0xb42eb1d2,0xb4b3b3a5,0xb6a0b56b,0xb666b58f,0xb872b7c9,
0x36493728,0x385038de,0x347c3565,0x363e3776,0x313e331e,0x335c34fa,0x29be2eb0,0x2c0c30b5,0xacc8a3a8,0xaebda566,0xb22fb04b,0xb455b20a,0xb4f1b406,0xb6dcb59d,0xb6b9b5d8,0xb898b807,
0x3697377e,0x38743904,0x34b635a9,0x367537b6,0x3182337a,0x339f3527,0x2a092f08,0x2c3230e1,0xad07a406,0xaefba598,0xb27fb083,0xb47cb241,0xb530b43a,0xb717b5cf,0xb70cb621,0xb8bdb828,
0x36e437d4,0x3897392a,0x34ee35ed,0x36ab37f5,0x31c633d6,0x33e23554,0x2a542f5f,0x2c57310c,0xad45a439,0xaf3aa5cb,0xb2cfb0bb,0xb4a4b279,0xb56eb46d,0xb752b601,0xb75db669,0xb8e1b84a,
0x37303814,0x38b9394e,0x3527362f,0x36e1381a,0x320a3418,0x34123580,0x2aa02fb6,0x2c7d3137,0xad84a46b,0xaf78a5fd,0xb31eb0f3,0xb4cbb2b0,0xb5acb4a0,0xb78cb632,0xb7adb6b1,0xb905b86b,
0x377c383e,0x38db3972,0x355f3672,0x37173838,0x324e3446,0x343435ac,0x2aeb3007,0x2ca23163,0xadc3a49d,0xafb6a62f,0xb36eb12b,0xb4f1b2e7,0xb5eab4d4,0xb7c6b663,0xb7fdb6f8,0xb928b88b,
0x38fd3996,0x39f33a91,0x374c3857,0x3874393e,0x345535d8,0x355d3730,0x2cc8318e,0x2df532e7,0xaff5a661,0xb0f3a7f3,0xb518b31e,0xb649b46a,0xb800b694,0xb8dbb808,0xb94bb8ab,0xba45b99b,
0x391e39b8,0x3a0f3aad,0x37813875,0x388c3959,0x34763604,0x357d375a,0x2cee31b9,0x2e1a3312,0xb01aa694,0xb112a813,0xb53fb356,0xb66fb485,0xb81cb6c5,0xb8f5b81f,0xb96db8cb,0xba61b9b7,
0x393e39da,0x3a2b3ac7,0x37b63893,0x38a53974,0x3497362f,0x359d3784,0x2d1331e5,0x2e40333d,0xb039a6c6,0xb131a82c,0xb565b38d,0xb694b4a0,0xb838b6f5,0xb90fb836,0xb98eb8ea,0xba7cb9d2,
0x395e39fb,0x3a453ae0,0x37ea38b0,0x38bd398e,0x34b9365b,0x35be37ad,0x2d393210,0x2e653368,0xb058a6f8,0xb150a845,0xb58cb3c3,0xb6b9b4bc,0xb854b725,0xb928b84c,0xb9aeb909,0xba97b9ed,
0x397d3a1b,0x3a5f3af9,0x380f38cd,0x38d539a8,0x34da3686,0x35de37d7,0x2d5e323b,0x2e8b3393,0xb077a72a,0xb16fa85e,0xb5b2b3fa,0xb6deb4d7,0xb870b755,0xb941b863,0xb9ceb927,0xbab0ba07,
0x399b3a3a,0x3a793b10,0x382838ea,0x38ed39c1,0x34fa36b1,0x35fe3800,0x2d843266,0x2eb033bd,0xb096a75d,0xb18ea877,0xb5d8b418,0xb703b4f1,0xb88bb784,0xb95ab879,0xb9edb945,0xbac9ba21,
0x39b93a58,0x3a913b26,0x38423906,0x390439da,0x351b36dc,0x361e3814,0x2daa3291,0x2ed633e8,0xb0b5a78f,0xb1ada890,0xb5feb434,0xb728b50c,0xb8a6b7b3,0xb972b88f,0xba0bb962,0xbae0ba3a,
0x39d73a75,0x3aa93b3c,0x385b3922,0x391b39f2,0x353c3706,0x363e3828,0x2dcf32bc,0x2efb3409,0xb0d4a7c1,0xb1cca8aa,0xb624b44f,0xb74cb527,0xb8c1b7e2,0xb98ab8a5,0xba29b97f,0xbaf7ba52,
0x3ac03b50,0x3b5e3bcb,0x39323a0a,0x39de3ab8,0x365e383c,0x375738d7,0x2f21341f,0x302634c8,0xb1eba8c3,0xb2e1a98c,0xb770b542,0xb846b615,0xb9a2b8bb,0xba51b960,0xbb0dba6a,0xbb9cbb11,
0x3ad73b63,0x3b6e3bd6,0x39493a22,0x39f23acb,0x367d3850,0x377638ea,0x2f463434,0x303934dd,0xb20aa8dc,0xb300a9a5,0xb795b55d,0xb857b62f,0xb9b9b8d0,0xba65b974,0xbb22ba81,0xbba9bb24,
0x3aec3b75,0x3b7d3bdf,0x395f3a39,0x3a063ade,0x369d3864,0x379538fd,0x2f6c3449,0x304b34f1,0xb229a8f5,0xb31ea9be,0xb7b8b577,0xb868b649,0xb9d0b8e5,0xba79b987,0xbb36ba97,0xbbb6bb35,
0x3b013b86,0x3b8c3be7,0x39753a4f,0x3a193af0,0x36bc3878,0x37b3390f,0x2f91345e,0x305e3506,0xb247a90e,0xb33da9d7,0xb7dcb592,0xb879b663,0xb9e7b8fa,0xba8cb99a,0xbb4abaad,0xbbc2bb46,
0x3b153b96,0x3b993bee,0x398a3a65,0x3a2d3b02,0x36dc388b,0x37d13921,0x2fb63473,0x3071351b,0xb266a927,0xb35ca9f0,0xb800b5ac,0xb88ab67d,0xb9fdb90f,0xba9fb9ad,0xbb5cbac3,0xbbccbb56,
0x3b283ba5,0x3ba63bf4,0x39a03a7a,0x3a3f3b13,0x36fb389e,0x37ef3933,0x2fdc3488,0x30833530,0xb285a940,0xb37aaa09,0xb811b5c7,0xb89bb697,0xba12b924,0xbab1b9c0,0xbb6dbad7,0xbbd6bb65,
0x3b3b3bb3,0x3bb23bf9,0x39b53a8f,0x3a523b24,0x371a38b2,0x38073945,0x3001349d,0x30963545,0xb2a4a959,0xb399aa22,0xb823b5e1,0xb8abb6b1,0xba28b938,0xbac3b9d2,0xbb7ebaeb,0xbbdfbb74,
0x3b4d3bc0,0x3bbd3bfc,0x39ca3aa4,0x3a643b34,0x373938c5,0x38153957,0x301334b3,0x30a9355a,0xb2c2a972,0xb3b7aa3b,0xb834b5fb,0xb8bcb6ca,0xba3cb94c,0xbad4b9e4,0xbb8dbaff,0xbbe6bb82,
0x20e921b2,0x31313204,0x1ead2020,0x2f14305e,0x1b121d1b,0x2b822d6b,0xe4817db,0x1ead282c,0x997f94b6,0xa9d7a502,0x9de49c52,0xae40ac96,0xa0849f76,0xb0c8afe8,0xa216a14d,0xb26cb19b,
0x275d2845,0x31cc32b6,0x2502262f,0x2fe830e1,0x214d23a8,0x2c322e0e,0x14b61de4,0x1f7628aa,0xa0209b12,0xaa87a598,0xa46ba27b,0xaefbad20,0xa6c6a598,0xb156b06a,0xa890a7f3,0xb32bb241,
0x2a222b1d,0x32663368,0x282c2927,0x305e3163,0x246b2661,0x2ca22eb0,0x17db20e9,0x20202927,0xa2df9de4,0xab36a62f,0xa75da566,0xafb6adaa,0xa9a5a8aa,0xb1e5b0e1,0xab9baaa0,0xb3e8b2e7,
0x2c4b2cfa,0x3300340c,0x29d72b36,0x30c831e5,0x262f2877,0x2d132f53,0x197f22df,0x208429a5,0xa4cfa020,0xabe6a6c6,0xa927a78f,0xb039ae33,0xabe6aa87,0xb273b156,0xad52aca2,0xb452b38d,
0x2d842e65,0x33993464,0x2b822ca2,0x31313266,0x27f329be,0x2d842ff5,0x1b12246b,0x20e92a22,0xa62fa14d,0xac4ba75d,0xaaa0a8dc,0xb096aebd,0xad13ac32,0xb300b1cc,0xaed6adf5,0xb4b0b418,
0x2ebd2fcf,0x341834bc,0x2c962daa,0x319b32e7,0x28dc2b04,0x2df5304b,0x1c522566,0x214d2aa0,0xa78fa27b,0xaca2a7f3,0xac0ca9f0,0xb0f3af46,0xae33ad20,0xb38db241,0xb02caf46,0xb50cb46a,
0x2ff5309c,0x34643512,0x2d6b2eb0,0x32043368,0x29be2c25,0x2e65309c,0x1d1b2661,0x21b22b1d,0xa877a3a8,0xacfaa845,0xacc8ab04,0xb150afcf,0xaf53ae0e,0xb40cb2b6,0xb0edb04b,0xb568b4bc,
0x30963150,0x34b03568,0x2e402fb6,0x326c33e8,0x2aa02cc8,0x2ed630ed,0x1de4275d,0x22162b9b,0xa927a46b,0xad52a890,0xad84ac0c,0xb1adb02c,0xb039aefb,0xb452b32b,0xb1adb0f3,0xb5c4b50c,
0x34fa35be,0x373e3826,0x32d53434,0x35063627,0x2f46313e,0x316333bd,0x227b2c0c,0x24cf2e01,0xadaaa8dc,0xb032ab36,0xb20ab071,0xb473b291,0xb497b39f,0xb6b4b598,0xb61eb55d,0xb867b7c6,
0x35453612,0x3784384c,0x333d3473,0x35393663,0x2fb6318e,0x319b3406,0x22df2c4b,0x25022e40,0xae01a927,0xb05eab82,0xb266b0b5,0xb4a0b2d5,0xb4ddb409,0xb6f5b5cf,0xb678b5ac,0xb88fb808,
0x358f3666,0x37c93872,0x33a534b3,0x356b36a0,0x301331df,0x31d2342e,0x23442c89,0x25342e7e,0xae59a972,0xb08aabcd,0xb2c2b0f9,0xb4ceb318,0xb521b443,0xb736b607,0xb6d0b5fb,0xb8b7b82c,
0x35d836b9,0x38073898,0x340634f1,0x359d36dc,0x304b322f,0x320a3455,0x23a82cc8,0x25662ebd,0xaeb0a9be,0xb0b5ac0c,0xb31eb13e,0xb4fab35c,0xb565b47c,0xb776b63e,0xb728b649,0xb8deb850,
0x3621370c,0x382838bd,0x343a3530,0x35cf3717,0x3083327f,0x3241347c,0x24062d07,0x25982efb,0xaf08aa09,0xb0e1ac32,0xb37ab182,0xb527b39f,0xb5a9b4b6,0xb7b6b675,0xb77eb697,0xb904b874,
0x3669375d,0x384a38e1,0x346d356e,0x36013752,0x30bb32cf,0x327934a4,0x24392d45,0x25cb2f3a,0xaf5faa54,0xb10cac57,0xb3d6b1c6,0xb554b3e2,0xb5edb4ee,0xb7f5b6ab,0xb7d4b6e4,0xb92ab897,
0x36b137ad,0x386b3905,0x34a035ac,0x3632378c,0x30f3331e,0x32b034cb,0x246b2d84,0x25fd2f78,0xafb6aaa0,0xb137ac7d,0xb418b20a,0xb580b412,0xb62fb527,0xb81ab6e1,0xb814b730,0xb94eb8b9,
0x36f837fd,0x388b3928,0x34d435ea,0x366337c6,0x312b336e,0x32e734f1,0x249d2dc3,0x262f2fb6,0xb007aaeb,0xb163aca2,0xb446b24e,0xb5acb434,0xb672b55f,0xb838b717,0xb83eb77c,0xb972b8db,
0x38ab394b,0x399b3a45,0x36943800,0x380838db,0x331e3518,0x346a3649,0x26612ff5,0x27f330f3,0xb18eacc8,0xb2e7adf5,0xb5d8b455,0xb730b55d,0xb857b74c,0xb93eb874,0xb996b8fd,0xba91b9f3,
0x38cb396d,0x39b73a61,0x36c5381c,0x381f38f5,0x3356353f,0x3485366f,0x2694301a,0x28133112,0xb1b9acee,0xb312ae1a,0xb604b476,0xb75ab57d,0xb875b781,0xb959b88c,0xb9b8b91e,0xbaadba0f,
0x38ea398e,0x39d23a7c,0x36f53838,0x3836390f,0x338d3565,0x34a03694,0x26c63039,0x282c3131,0xb1e5ad13,0xb33dae40,0xb62fb497,0xb784b59d,0xb893b7b6,0xb974b8a5,0xb9dab93e,0xbac7ba2b,
0x390939ae,0x39ed3a97,0x37253854,0x384c3928,0x33c3358c,0x34bc36b9,0x26f83058,0x28453150,0xb210ad39,0xb368ae65,0xb65bb4b9,0xb7adb5be,0xb8b0b7ea,0xb98eb8bd,0xb9fbb95e,0xbae0ba45,
0x392739ce,0x3a073ab0,0x37553870,0x38633941,0x33fa35b2,0x34d736de,0x272a3077,0x285e316f,0xb23bad5e,0xb393ae8b,0xb686b4da,0xb7d7b5de,0xb8cdb80f,0xb9a8b8d5,0xba1bb97d,0xbaf9ba5f,
0x394539ed,0x3a213ac9,0x3784388b,0x3879395a,0x341835d8,0x34f13703,0x275d3096,0x2877318e,0xb266ad84,0xb3bdaeb0,0xb6b1b4fa,0xb800b5fe,0xb8eab828,0xb9c1b8ed,0xba3ab99b,0xbb10ba79,
0x39623a0b,0x3a3a3ae0,0x37b338a6,0x388f3972,0x343435fe,0x350c3728,0x278f30b5,0x289031ad,0xb291adaa,0xb3e8aed6,0xb6dcb51b,0xb814b61e,0xb906b842,0xb9dab904,0xba58b9b9,0xbb26ba91,
0x397f3a29,0x3a523af7,0x37e238c1,0x38a5398a,0x344f3624,0x3527374c,0x27c130d4,0x28aa31cc,0xb2bcadcf,0xb409aefb,0xb706b53c,0xb828b63e,0xb922b85b,0xb9f2b91b,0xba75b9d7,0xbb3cbaa9,
0x3a6a3b0d,0x3b113b9c,0x38bb39a2,0x39603a51,0x35423770,0x36153846,0x28c331eb,0x298c32e1,0xb41faf21,0xb4c8b026,0xb83cb65e,0xb8d7b757,0xba0ab932,0xbab8b9de,0xbb50bac0,0xbbcbbb5e,
0x3a813b22,0x3b243ba9,0x38d039b9,0x39743a65,0x355d3795,0x362f3857,0x28dc320a,0x29a53300,0xb434af46,0xb4ddb039,0xb850b67d,0xb8eab776,0xba22b949,0xbacbb9f2,0xbb63bad7,0xbbd6bb6e,
0x3a973b36,0x3b353bb6,0x38e539d0,0x39873a79,0x357737b8,0x36493868,0x28f53229,0x29be331e,0xb449af6c,0xb4f1b04b,0xb864b69d,0xb8fdb795,0xba39b95f,0xbadeba06,0xbb75baec,0xbbdfbb7d,
0x3aad3b4a,0x3b463bc2,0x38fa39e7,0x399a3a8c,0x359237dc,0x36633879,0x290e3247,0x29d7333d,0xb45eaf91,0xb506b05e,0xb878b6bc,0xb90fb7b3,0xba4fb975,0xbaf0ba19,0xbb86bb01,0xbbe7bb8c,
0x3ac33b5c,0x3b563bcc,0x390f39fd,0x39ad3a9f,0x35ac3800,0x367d388a,0x29273266,0x29f0335c,0xb473afb6,0xb51bb071,0xb88bb6dc,0xb921b7d1,0xba65b98a,0xbb02ba2d,0xbb96bb15,0xbbeebb99,
0x3ad73b6d,0x3b653bd6,0x39243a12,0x39c03ab1,0x35c73811,0x3697389b,0x29403285,0x2a09337a,0xb488afdc,0xb530b083,0xb89eb6fb,0xb933b7ef,0xba7ab9a0,0xbb13ba3f,0xbba5bb28,0xbbf4bba6,
0x3aeb3b7e,0x3b743bdf,0x39383a28,0x39d23ac3,0x35e13823,0x36b138ab,0x295932a4,0x2a223399,0xb49db001,0xb545b096,0xb8b2b71a,0xb945b807,0xba8fb9b5,0xbb24ba52,0xbbb3bb3b,0xbbf9bbb2,
0x3aff3b8d,0x3b823be6,0x394c3a3c,0x39e43ad4,0x35fb3834,0x36ca38bc,0x297232c2,0x2a3b33b7,0xb4b3b013,0xb55ab0a9,0xb8c5b739,0xb957b815,0xbaa4b9ca,0xbb34ba64,0xbbc0bb4d,0xbbfcbbbd,
0x39b839ba,0x3a973ab5,0x39b339b5,0x3a583a78,0x39af39b1,0x3a153a37,0x39aa39ad,0x39cd39f2,0x39a639a8,0x398239a8,0x39a139a4,0x3933395b,0x399d399f,0x38e03909,0x3999399b,0x388938b5,
0xb979b972,0xb865b832,0xb986b980,0xb8c7b896,0xb994b98d,0xb924b8f6,0xb9a1b99b,0xb97db951,0xb9afb9a8,0xb9d2b9a8,0xb9bcb9b5,0xba21b9fa,0xb9c9b9c3,0xba6bba47,0xb9d6b9d0,0xbab0ba8e,
0xb9f4b9fe,0xbac7bae9,0xb9dfb9e9,0xba7ebaa3,0xb9c9b9d4,0xba2dba56,0xb9b3b9be,0xb9d6ba02,0xb99db9a8,0xb979b9a8,0xb986b992,0xb916b948,0xb970b97b,0xb8adb8e2,0xb958b964,0xb840b877,
0x39373927,0x381a37b7,0x39583948,0x38943858,0x39793969,0x390738ce,0x39993989,0x3974393e,0x39b839a8,0x39da39a8,0x39d639c7,0x3a393a0b,0x39f439e5,0x3a903a65,0x3a113a02,0x3ade3ab8,
0x3a2d3a3f,0x3af43b1a,0x3a093a1b,0x3aa23acc,0x39e339f6,0x3a453a74,0x39bc39d0,0x39df3a13,0x399439a8,0x397039a8,0x396b3980,0x38f83935,0x39413956,0x387a38ba,0x3916392b,0x37e83838,
0xb8f3b8d8,0xb79bb705,0xb929b90e,0xb85fb817,0xb95db943,0xb8eab8a6,0xb990b976,0xb96bb92b,0xb9c0b9a8,0xb9e3b9a8,0xb9f0b9d8,0xba50ba1b,0xba1dba07,0xbab3ba83,0xba49ba33,0xbb0abae0,
0xba64ba7c,0xbb1ebb46,0xba31ba4b,0xbac4baf3,0xb9fcba17,0xba5cba92,0xb9c5b9e1,0xb9e7ba23,0xb98bb9a8,0xb966b9a8,0xb94fb96d,0xb8dbb922,0xb911b930,0xb845b891,0xb8d1b8f1,0xb74eb7ee,
0x38ad3887,0x36ff364e,0x38f838d3,0x382a37ac,0x3941391d,0x38cc387c,0x39863964,0x39623918,0x39c939a8,0x39eb39a8,0x3a0939e9,0x3a673a2b,0x3a453a27,0x3ad53aa0,0x3a7e3a62,0x3b323b05,
0x3b453b6e,0x3bbc3bdd,0x3ae53b17,0x3b573b8f,0x3a733aae,0x3ac73b14,0x39f03a33,0x3a113a71,0x395d39a8,0x393739a8,0x38bc390e,0x384038bf,0x380f3867,0x365f3775,0x36af376a,0x341a3540,
0xb65fb593,0xb389b115,0xb7e8b726,0xb625b4f9,0xb8adb852,0xb830b748,0xb958b905,0xb933b8b5,0xb9f4b9a8,0xba15b9a8,0xba7eba3b,0xbad1ba78,0xbaf4babc,0xbb63bb20,0xbb57bb28,0xbbc6bb9b,
0xbb68bb91,0xbbd0bbed,0xbb04bb39,0xbb6fbba6,0xba89bac9,0xbadbbb2b,0xb9f8ba43,0xba19ba7f,0xb954b9a8,0xb92eb9a8,0xb89eb8fb,0xb820b8ab,0xb7b2b83d,0xb5ebb71b,0xb60eb6e3,0xb2deb4b1,
0x35bc34d5,0x32322f0e,0x377a369e,0x35b13469,0x388e3828,0x380f36ee,0x394f38f1,0x392938a0,0x39fc39a8,0x3a1d39a8,0x3a933a4b,0x3ae53a87,0x3b133ad6,0x3b7a3b36,0x3b783b49,0x3bd93bb1,
0x3b873baf,0x3be13bf8,0x3b213b58,0x3b853bbb,0x3a9e3ae3,0x3aee3b41,0x3a003a52,0x3a213a8e,0x394a39a8,0x392439a8,0x387f38e7,0x37fe3896,0x37423812,0x357636c1,0x356a3659,0x31853420,
0xb517b414,0xb0d7abd9,0xb70ab614,0xb53ab3ae,0xb86fb7f9,0xb7ddb693,0xb946b8dd,0xb91fb88c,0xba04b9a8,0xba25b9a8,0xbaa9ba5a,0xbaf7ba95,0xbb2fbaf0,0xbb90bb4b,0xbb96bb67,0xbbe8bbc4,
0xbba3bbc9,0xbbefbbff,0xbb3dbb74,0xbb9abbcd,0xbab3bafc,0xbb01bb55,0xba09ba62,0xba29ba9c,0xb941b9a8,0xb91bb9a8,0xb85fb8d3,0xb7bdb881,0xb6d2b7cd,0xb4ffb665,0xb4c3b5ce,0xb029b31b,
0x346f32a1,0x2ef52248,0x36993587,0x34c33288,0x385037a1,0x379b3637,0x393c38c9,0x39163877,0x3a0d39a8,0x3a2d39a8,0x3abd3a69,0x3b0a3aa3,0x3b4a3b08,0x3ba33b5f,0x3bb03b82,0x3bf43bd5,
0x3bf83c00,0x3bf93bd4,0x3bac3bdc,0x3be43bfe,0x3b133b69,0x3b543bab,0x3a313aaa,0x3a503ae0,0x391139a8,0x38ea39a8,0x377a386d,0x366b3817,0x34873608,0x313b348d,0x2d9731f4,0xad65291b,
0xac3828b6,0x2ec33365,0xb44bb160,0xb0bea57f,0xb759b5da,0xb648b45d,0xb90cb862,0xb8e5b80d,0xba35b9a8,0xba54b9a8,0xbb1bbab1,0xbb5cbae6,0xbbb5bb72,0xbbe9bbb2,0xbbfcbbe3,0xbbf5bc00,
0xbbfebbfc,0xbbefbbbc,0xbbbdbbe9,0xbbeebc00,0xbb24bb7b,0xbb63bbb9,0xba39bab8,0xba58baed,0xb907b9a8,0xb8e0b9a8,0xb737b858,0xb625b802,0xb40eb5ab,0xb042b42c,0xa9b1b0cb,0x30109a48,
0x25e4ad7e,0xb0beb475,0x33a23036,0x2f8ba3db,0x3715357c,0x360233f7,0x3902384d,0x38db37ee,0x3a3d39a8,0x3a5c39a8,0x3b2c3abf,0x3b6a3af3,0x3bc53b84,0x3bf23bc0,0x3bff3bee,0x3be93c00,
0x3c003bf4,0x3be23ba0,0x3bcc3bf3,0x3bf53bff,0x3b353b8c,0x3b713bc6,0x3a413ac6,0x3a603af9,0x38fd39a8,0x38d639a8,0x36f43842,0x35df37d8,0x3328354c,0x2e913396,0x16482f40,0xb16ca852,
0x251b304e,0x32193534,0xb2adae14,0xad972aac,0xb6d2b51d,0xb5bcb334,0xb8f8b838,0xb8d1b7c2,0xba45b9a8,0xba64b9a8,0xbb3dbacc,0xbb78baff,0xbbd3bb95,0xbbf8bbcb,0xbc00bbf7,0xbbdabbfd,
0xbbfebbe6,0xbbd2bb80,0xbbd9bbfa,0xbbfbbbfb,0xbb45bb9d,0xbb7fbbd1,0xba49bad3,0xba67bb05,0xb8f3b9a8,0xb8ccb9a8,0xb6afb82d,0xb599b7ac,0xb232b4ed,0xac9cb2d2,0x294dace7,0x32c62c83,
0xac06b1db,0xb371b5f1,0x31b62b75,0x2b43adb0,0x368d34bd,0x3576326f,0x38ee3822,0x38c73796,0x3a4d39a8,0x3a6b39a8,0x3b4c3ad9,0x3b853b0b,0x3bdf3ba4,0x3bfd3bd6,0x3bfc3bfd,0x3bc83bf8,
0x3bbd3b5a,0x3b473a99,0x3bfe3bf4,0x3bf93bbe,0x3b8b3bdb,0x3bb83bf7,0x3a6f3b11,0x3a8c3b3e,0x38c139a8,0x389939a8,0x35523780,0x343236cc,0x294d320d,0xad332de2,0xb40eaedc,0xb6a4b408,
0x346336aa,0x36f438b0,0xa6ad3004,0x2e2d3451,0xb52fb1aa,0xb40ead1a,0xb8bcb76a,0xb894b6b5,0xba73b9a8,0xba90b9a8,0xbb92bb17,0xbbbdbb43,0xbbffbbe0,0xbbf6bbf9,0xbbb2bbf0,0xbb35bbb4,
0xbba5bb30,0xbb21ba5e,0xbc00bbeb,0xbbf3bbaa,0xbb98bbe4,0xbbc2bbfb,0xba76bb1d,0xba93bb49,0xb8b7b9a8,0xb88eb9a8,0xb50bb753,0xb3d3b69e,0xa17fb147,0x2f27ac51,0x34b73099,0x37423499,
0xb50bb75e,0xb790b900,0x9cb6b12e,0xb010b4e1,0x34e730e4,0x33892b11,0x38b2373d,0x38893687,0x3a7a39a8,0x3a9739a8,0x3b9e3b22,0x3bc63b4e,0x3c003be8,0x3bef3bfd,0x3b983be5,0x3b0d3b9e,
0x3b893b02,0x3af73a1f,0x3c003bdf,0x3beb3b93,0x3ba33bec,0x3bcb3bfe,0x3a7e3b28,0x3a9b3b53,0x38ad39a8,0x388439a8,0x34c33726,0x33403670,0xa51b3080,0xb08d297f,0xb55eb1c3,0xb7ddb529,
0x35b13807,0x3815394d,0x28843257,0x31093570,0xb49fb01d,0xb2f7a7da,0xb8a8b710,0xb87fb659,0xba81b9a8,0xba9eb9a8,0xbba9bb2e,0xbbcfbb58,0xbbffbbef,0xbbe6bbff,0xbb7abbd7,0xbae1bb86,
0xbb6abad0,0xbacbb9dc,0xbbfdbbd0,0xbbe1bb79,0xbbaebbf2,0xbbd3bc00,0xba85bb33,0xbaa2bb5d,0xb8a3b9a8,0xb87ab9a8,0xb47bb6f9,0xb2adb642,0x2a7aaf72,0x3185a4b6,0x360232ea,0x383a35b6,
0xb654b85d,0xb85fb996,0xac38b37d,0xb201b5fd,0x34572eaa,0x32631e48,0x389e36e3,0x3874362b,0x3a8939a8,0x3aa539a8,0x3bb33b39,0x3bd73b62,0x3bfc3bf5,0x3bdc3c00,0x3b593bc7,0x3ab33b6b,
0x39b739b9,0x3a883aa6,0x39b239b4,0x3a483a68,0x39ae39b0,0x3a033a26,0x39a939ab,0x39bb39e0,0x39a539a7,0x396e3995,0x39a039a3,0x391e3947,0x399c399e,0x38ca38f5,0x3997399a,0x3873389f,
0xb97cb975,0xb87eb84c,0xb98ab983,0xb8deb8ae,0xb997b991,0xb93bb90d,0xb9a5b99e,0xb993b967,0xb9b2b9ab,0xb9e6b9bd,0xb9bfb9b9,0xba34ba0e,0xb9ccb9c6,0xba7dba59,0xb9d9b9d3,0xbac0ba9f,
0xb9efb9f9,0xbab6bad9,0xb9d9b9e4,0xba6aba91,0xb9c4b9cf,0xba18ba42,0xb9aeb9b9,0xb9bfb9ec,0xb997b9a3,0xb961b991,0xb981b98c,0xb8fcb92f,0xb96ab975,0xb892b8c8,0xb953b95e,0xb824b85c,
0x3940392f,0x383937f6,0x39613950,0x38b13876,0x39813971,0x392338eb,0x39a03991,0x398e395a,0x39bf39b0,0x39f339c1,0x39de39cf,0x3a4f3a22,0x39fb39ec,0x3aa43a7b,0x3a183a0a,0x3af03acb,
0x3a243a36,0x3ae13b07,0x39ff3a12,0x3a8b3ab7,0x39d939ec,0x3a2c3a5d,0x39b239c6,0x39c439f9,0x398a399e,0x3953398c,0x39613975,0x38d93917,0x3936394b,0x3859389a,0x390b3921,0x37a43816,
0xb901b8e6,0xb7e6b750,0xb936b91c,0xb883b83c,0xb96ab950,0xb90bb8c8,0xb99cb983,0xb98ab94b,0xb9ccb9b4,0xb9ffb9c6,0xb9fbb9e4,0xba6aba36,0xba28ba12,0xbacaba9b,0xba53ba3e,0xbb1dbaf5,
0xba57ba70,0xbb09bb33,0xba24ba3e,0xbaabbadc,0xb9efba0a,0xba40ba77,0xb9b7b9d3,0xb9c8ba05,0xb97cb99a,0xb944b988,0xb940b95e,0xb8b6b8fe,0xb901b921,0xb81eb86b,0xb8c0b8e1,0xb6fcb79e,
0x38c0389a,0x375636a7,0x390b38e6,0x38543800,0x3953392f,0x38f238a4,0x39973975,0x3985393d,0x39d939b9,0x3a0c39ca,0x3a1839f9,0x3a843a4a,0x3a533a36,0x3aed3abb,0x3a8b3a70,0x3b473b1c,
0x3b2e3b5a,0x3ba63bce,0x3aca3afe,0x3b373b74,0x3a533a91,0x3a9d3aef,0x39cc3a12,0x39de3a42,0x39363983,0x38fc3971,0x389238e6,0x37fb3880,0x37c5383c,0x35d136eb,0x3651370d,0x330934ae,
0xb6c3b5fa,0xb460b251,0xb824b788,0xb6b8b590,0xb8d9b880,0xb873b7d5,0xb981b92f,0xb96eb8f5,0xba18b9cf,0xba48b9e0,0xba9dba5d,0xbafabaa6,0xbb0fbad9,0xbb80bb43,0xbb6cbb40,0xbbd8bbb2,
0xbb51bb7d,0xbbbdbbe0,0xbae7bb1f,0xbb4ebb8c,0xba66baa9,0xbaafbb04,0xb9d1ba1e,0xb9e2ba4e,0xb928b97e,0xb8edb96c,0xb86eb8cd,0xb7afb866,0xb74bb80b,0xb54fb684,0xb5a2b679,0xb197b411,
0x362e3549,0x338330de,0x37e6370d,0x3651350e,0x38c0385c,0x38593788,0x397c3921,0x396a38e6,0x3a2439d3,0x3a5339e4,0x3ab63a70,0x3b0f3ab7,0x3b2e3af5,0x3b973b5a,0x3b8d3b61,0x3be83bc7,
0x3b703b9c,0x3bd03bef,0x3b033b3d,0x3b653ba2,0x3a793ac1,0x3ac03b19,0x39d53a2a,0x39e63a59,0x3919397a,0x38de3967,0x384938b4,0x3761384c,0x36cf37b4,0x34cc361d,0x34f035e2,0x302332e4,
0xb596b496,0xb244aecf,0xb783b690,0xb5e8b48a,0xb8a7b836,0xb83eb73a,0xb978b912,0xb965b8d7,0xba30b9d7,0xba5fb9e8,0xbacdba82,0xbb23bac8,0xbb4cbb10,0xbbacbb6f,0xbbaabb7f,0xbbf4bbd8,
0xbb8dbbb7,0xbbe0bbf9,0xbb1dbb5a,0xbb7abbb5,0xba8bbad9,0xbad0bb2d,0xb9d9ba36,0xb9eaba65,0xb90bb975,0xb8cfb963,0xb824b89a,0xb713b831,0xb651b750,0xb447b5b3,0xb43bb549,0xad58b1a4,
0x34fc33c0,0x31032bc0,0x371e3611,0x357e3405,0x388d3811,0x382436eb,0x39733903,0x396138c8,0x3a3c39db,0x3a6a39ec,0x3ae43a94,0x3b373ad9,0x3b673b2a,0x3bbe3b83,0x3bc33b9a,0x3bfc3be7,
0x3bed3bff,0x3bff3bea,0x3b8d3bc7,0x3bcc3bf5,0x3ae13b40,0x3b1d3b83,0x39ef3a70,0x39ff3a9b,0x38c0395e,0x3883394b,0x36c33816,0x357e3750,0x33833549,0x2e84332e,0x28cf3061,0xb0aca5b2,
0xaf7ea376,0x29663166,0xb514b2fd,0xb2bfad71,0xb809b69b,0xb734b555,0xb95cb8b9,0xb949b87b,0xba75b9f1,0xbaa1ba01,0xbb49bae9,0xbb8bbb25,0xbbcfbb96,0xbbf9bbd2,0xbc00bbf2,0xbbe3bbfe,
0xbbf6bc00,0xbbfcbbda,0xbb9fbbd6,0xbbd8bbfb,0xbaf0bb52,0xbb2cbb92,0xb9f3ba7b,0xba03baa6,0xb8b1b95a,0xb873b947,0xb673b7f6,0xb52cb718,0xb276b4de,0xac5eb251,0x2052ae39,0x321f2bf2,
0x2cf4a806,0xad3fb2d8,0x34a831ee,0x31e22a93,0x37db364b,0x36fc3502,0x395738a9,0x3944386b,0x3a8039f5,0x3aab3a05,0x3b5b3af8,0x3b993b33,0x3bdd3ba7,0x3bfd3bdd,0x3bff3bfa,0x3bd13bf9,
0x3bfd3bfd,0x3bf53bc6,0x3baf3be3,0x3be23bff,0x3b003b64,0x3b393ba0,0x39f73a86,0x3a083ab0,0x38a23955,0x38633942,0x362237bf,0x34d836e0,0x31663472,0x286b3172,0xaaf82b5c,0xb390ae84,
0xa8cf2cf4,0x2fc93423,0xb43bb0de,0xb103a484,0xb7a4b5fa,0xb6c3b4ae,0xb953b89a,0xb940b85c,0xba8bb9f9,0xbab6ba0a,0xbb6cbb07,0xbba6bb40,0xbbe8bbb7,0xbc00bbe7,0xbbfabbff,0xbbbabbf1,
0xbc00bbf6,0xbbebbbae,0xbbbebbed,0xbbebbc00,0xbb0fbb74,0xbb47bbad,0xb9fbba91,0xba0cbabb,0xb892b950,0xb854b93d,0xb5d1b788,0xb484b6a7,0xb055b405,0x9248b093,0x2e6ba484,0x347e3086,
0x98b6afe2,0xb128b4d8,0x339c2f97,0x3023a420,0x376c35a8,0x368a345a,0x394e388b,0x393b384c,0x3a9639fd,0x3ac03a0e,0x3b7c3b16,0x3bb33b4d,0x3bf23bc5,0x3c003bef,0x3bf03c00,0x3ba03be5,
0x3bde3b91,0x3b8a3af7,0x3bf23bff,0x3c003be3,0x3b533bb9,0x3b823bdf,0x3a103ac5,0x3a203aec,0x38443939,0x38033925,0x342f366d,0x31b03584,0xa8392f65,0xb15a1d7f,0xb531b1c9,0xb7e0b55b,
0x3269358a,0x35a83819,0xae842a61,0x205231e2,0xb651b405,0xb567b15a,0xb936b83c,0xb923b7f6,0xbacaba12,0xbaf0ba22,0xbbbebb5a,0xbbe3bb88,0xbbfdbbf5,0xbbddbc00,0xbb81bbd6,0xbadfbb7c,
0xbbcebb70,0xbb6dbac6,0xbbf8bbfb,0xbbffbbd6,0xbb60bbc4,0xbb8dbbe7,0xba14bacf,0xba24baf5,0xb834b934,0xb7e6b921,0xb3b4b634,0xb103b549,0x2c44ada3,0x326925b2,0x35e23309,0x384135f4,
0xb3a8b63a,0xb63fb869,0x2cc2ad58,0xa89db2f0,0x3617335f,0x352c30ac,0x3931382c,0x391e37d5,0x3ad43a16,0x3afa3a26,0x3bc93b66,0x3bea3b92,0x3bf93bfa,0x3bcf3bff,0x3b5f3bc5,0x3aad3b5d,
0x3bba3b4c,0x3b4d3a93,0x3bfc3bf6,0x3bfd3bc7,0x3b6c3bce,0x3b973bed,0x3a183ad9,0x3a283afe,0x3824392f,0x37c5391c,0x330935fa,0x3055350e,0xae6b2bc0,0xb377aa61,0xb690b423,0xb890b68a,
0x347236e5,0x36d438b6,0xa9fd2f7e,0x2c1233fd,0xb5dcb2b3,0xb4f0affb,0xb92db81c,0xb919b7b4,0xbaddba1a,0xbb03ba2a,0xbbd3bb72,0xbbf0bb9c,0xbbf2bbfe,0xbbbfbbfc,0xbb38bbaf,0xba77bb3c,
0xbba4bb23,0xbb2aba5b,0xbbffbbee,0xbbfabbb6,0xbb77bbd7,0xbba1bbf3,0xba1cbae2,0xba2cbb07,0xb813b92a,0xb7a4b917,0xb25db5bf,0xaf4cb4d2,0x3048a839,0x34412cf4,0x373a34c0,0x38dc371e,
0xb50eb78e,0xb767b901,0x24e9b0d1,0xadd5b484,0x35a23207,0x34b42e9d,0x3928380b,0x39143793,0x3ae73a1e,0x3b0c3a2e,0x3bdb3b7d,0x3bf53ba6,0x3be93c00,0x3bad3bf7,0x3b0d3b97,0x3a3e3b18,
0xb999b996,0xb889b85d,0xb99db99b,0xb8e0b8b5,0xb9a1b99f,0xb933b909,0xb9a6b9a4,0xb982b95b,0xb9aab9a8,0xb9cdb9a8,0xb9afb9ad,0xba15b9f2,0xb9b3b9b1,0xba58ba37,0xb9b8b9b5,0xba97ba78,
0xb9d6b9dc,0xbab0bad0,0xb9c9b9d0,0xba6bba8e,0xb9bcb9c3,0xba21ba47,0xb9afb9b5,0xb9d2b9fa,0xb9a1b9a8,0xb97db9a8,0xb994b99b,0xb924b951,0xb986b98d,0xb8c7b8f6,0xb979b980,0xb865b896,
0x3958394d,0x38403807,0x39703964,0x38ad3877,0x3986397b,0x391638e2,0x399d3992,0x39793948,0x39b339a8,0x39d639a8,0x39c939be,0x3a2d3a02,0x39df39d4,0x3a7e3a56,0x39f439e9,0x3ac73aa3,
0x3a113a1f,0x3ade3b02,0x39f43a02,0x3a903ab8,0x39d639e5,0x3a393a65,0x39b839c7,0x39da3a0b,0x399939a8,0x397439a8,0x39793989,0x3907393e,0x39583969,0x389438ce,0x39373948,0x381a3858,
0xb916b900,0xb7e8b75e,0xb941b92b,0xb87ab838,0xb96bb956,0xb8f8b8ba,0xb994b980,0xb970b935,0xb9bcb9a8,0xb9dfb9a8,0xb9e3b9d0,0xba45ba13,0xba09b9f6,0xbaa2ba74,0xba2dba1b,0xbaf4bacc,
0xba49ba5e,0xbb0abb30,0xba1dba33,0xbab3bae0,0xb9f0ba07,0xba50ba83,0xb9c0b9d8,0xb9e3ba1b,0xb990b9a8,0xb96bb9a8,0xb95db976,0xb8eab92b,0xb929b943,0xb85fb8a6,0xb8f3b90e,0xb79bb817,
0x38d138b0,0x374e36aa,0x391138f1,0x384537ee,0x394f3930,0x38db3891,0x398b396d,0x39663922,0x39c539a8,0x39e739a8,0x39fc39e1,0x3a5c3a23,0x3a313a17,0x3ac43a92,0x3a643a4b,0x3b1e3af3,
0x3a7e3a99,0x3b323b5a,0x3a453a62,0x3ad53b05,0x3a093a27,0x3a673aa0,0x39c939e9,0x39eb3a2b,0x398639a8,0x396239a8,0x39413964,0x38cc3918,0x38f8391d,0x382a387c,0x38ad38d3,0x36ff37ac,
0xb6afb5f1,0xb41ab1db,0xb80fb76a,0xb65fb540,0xb8bcb867,0xb840b775,0xb95db90e,0xb937b8bf,0xb9f0b9a8,0xba11b9a8,0xba73ba33,0xbac7ba71,0xbae5baae,0xbb57bb14,0xbb45bb17,0xbbbcbb8f,
0xbb57bb80,0xbbc6bbe6,0xbaf4bb28,0xbb63bb9b,0xba7ebabc,0xbad1bb20,0xb9f4ba3b,0xba15ba78,0xb958b9a8,0xb933b9a8,0xb8adb905,0xb830b8b5,0xb7e8b852,0xb625b748,0xb65fb726,0xb389b4f9,
0x360e3534,0x32de304e,0x37b236e3,0x35eb34b1,0x389e383d,0x3820371b,0x395438fb,0x392e38ab,0x39f839a8,0x3a1939a8,0x3a893a43,0x3adb3a7f,0x3b043ac9,0x3b6f3b2b,0x3b683b39,0x3bd03ba6,
0x3b783ba0,0x3bd93bf4,0x3b133b49,0x3b7a3bb1,0x3a933ad6,0x3ae53b36,0x39fc3a4b,0x3a1d3a87,0x394f39a8,0x392939a8,0x388e38f1,0x380f38a0,0x377a3828,0x35b136ee,0x35bc369e,0x32323469,
0xb56ab475,0xb185ad7e,0xb742b659,0xb576b420,0xb87fb812,0xb7feb6c1,0xb94ab8e7,0xb924b896,0xba00b9a8,0xba21b9a8,0xba9eba52,0xbaeeba8e,0xbb21bae3,0xbb85bb41,0xbb87bb58,0xbbe1bbbb,
0xbb96bbbc,0xbbe8bbfc,0xbb2fbb67,0xbb90bbc4,0xbaa9baf0,0xbaf7bb4b,0xba04ba5a,0xba25ba95,0xb946b9a8,0xb91fb9a8,0xb86fb8dd,0xb7ddb88c,0xb70ab7f9,0xb53ab693,0xb517b614,0xb0d7b3ae,
0x34c33365,0x302928b6,0x36d235ce,0x34ff331b,0x385f37cd,0x37bd3665,0x394138d3,0x391b3881,0x3a0939a8,0x3a2939a8,0x3ab33a62,0x3b013a9c,0x3b3d3afc,0x3b9a3b55,0x3ba33b74,0x3bef3bcd,
0x3bb03bd4,0x3bf43c00,0x3b4a3b82,0x3ba33bd5,0x3abd3b08,0x3b0a3b5f,0x3a0d3a69,0x3a2d3aa3,0x393c39a8,0x391639a8,0x385038c9,0x379b3877,0x369937a1,0x34c33637,0x346f3587,0x2ef53288,
0xad972248,0x2d6532a1,0xb487b1f4,0xb13ba91b,0xb77ab608,0xb66bb48d,0xb911b86d,0xb8eab817,0xba31b9a8,0xba50b9a8,0xbb13baaa,0xbb54bae0,0xbbacbb69,0xbbe4bbab,0xbbf8bbdc,0xbbf9bbfe,
0xbbfcbbff,0xbbf5bbc9,0xbbb5bbe3,0xbbe9bc00,0xbb1bbb72,0xbb5cbbb2,0xba35bab1,0xba54bae6,0xb90cb9a8,0xb8e5b9a8,0xb759b862,0xb648b80d,0xb44bb5da,0xb0beb45d,0xac38b160,0x2ec3a57f,
0x29b1abd9,0xb010b414,0x340e30cb,0x30421a48,0x373735ab,0x3625342c,0x39073858,0x38e03802,0x3a3939a8,0x3a5839a8,0x3b243ab8,0x3b633aed,0x3bbd3b7b,0x3bee3bb9,0x3bfe3be9,0x3bef3c00,
0x3bff3bf8,0x3be93baf,0x3bc53bee,0x3bf23c00,0x3b2c3b84,0x3b6a3bc0,0x3a3d3abf,0x3a5c3af3,0x390239a8,0x38db39a8,0x3715384d,0x360237ee,0x33a2357c,0x2f8b33f7,0x25e43036,0xb0bea3db,
0x96482f0e,0x316c34d5,0xb328af40,0xae912852,0xb6f4b54c,0xb5dfb396,0xb8fdb842,0xb8d6b7d8,0xba41b9a8,0xba60b9a8,0xbb35bac6,0xbb71baf9,0xbbccbb8c,0xbbf5bbc6,0xbc00bbf3,0xbbe2bbff,
0xbc00bbed,0xbbdabb91,0xbbd3bbf7,0xbbf8bbfd,0xbb3dbb95,0xbb78bbcb,0xba45bacc,0xba64baff,0xb8f8b9a8,0xb8d1b9a8,0xb6d2b838,0xb5bcb7c2,0xb2adb51d,0xad97b334,0x251bae14,0x32192aac,
0xa94db115,0xb2c6b593,0x32322ce7,0x2c9cac83,0x36af34ed,0x359932d2,0x38f3382d,0x38cc37ac,0x3a4939a8,0x3a6739a8,0x3b453ad3,0x3b7f3b05,0x3bd93b9d,0x3bfb3bd1,0x3bfe3bfa,0x3bd23bfb,
0x3bfc3bdd,0x3bc83b6e,0x3bdf3bfd,0x3bfd3bf8,0x3b4c3ba4,0x3b853bd6,0x3a4d3ad9,0x3a6b3b0b,0x38ee39a8,0x38c739a8,0x368d3822,0x35763796,0x31b634bd,0x2b43326f,0xac062b75,0xb371adb0,
0x340e364e,0x36a43887,0xa94d2edc,0x2d333408,0xb552b20d,0xb432ade2,0xb8c1b780,0xb899b6cc,0xba6fb9a8,0xba8cb9a8,0xbb8bbb11,0xbbb8bb3e,0xbbfebbdb,0xbbf9bbf7,0xbbbdbbf4,0xbb47bbbe,
0xbbb2bb46,0xbb35ba7c,0xbbffbbf0,0xbbf6bbb4,0xbb92bbe0,0xbbbdbbf9,0xba73bb17,0xba90bb43,0xb8bcb9a8,0xb894b9a8,0xb52fb76a,0xb40eb6b5,0xa6adb1aa,0x2e2dad1a,0x34633004,0x36f43451,
0xb4b7b705,0xb742b8d8,0x217fb099,0xaf27b499,0x350b3147,0x33d32c51,0x38b73753,0x388e369e,0x3a7639a8,0x3a9339a8,0x3b983b1d,0x3bc23b49,0x3c003be4,0x3bf33bfb,0x3ba53beb,0x3b213baa,
0x3b983b1a,0x3b0d3a3f,0x3c003be5,0x3bef3b9e,0x3b9e3be8,0x3bc63bfd,0x3a7a3b22,0x3a973b4e,0x38b239a8,0x388939a8,0x34e7373d,0x33893687,0x9cb630e4,0xb0102b11,0xb50bb12e,0xb790b4e1,
0x355e37b7,0x37dd3927,0x251b31c3,0x308d3529,0xb4c3b080,0xb340a97f,0xb8adb726,0xb884b670,0xba7eb9a8,0xba9bb9a8,0xbba3bb28,0xbbcbbb53,0xbc00bbec,0xbbebbbfe,0xbb89bbdf,0xbaf7bb93,
0xbb7abae9,0xbae1b9fe,0xbbffbbd7,0xbbe6bb86,0xbba9bbef,0xbbcfbbff,0xba81bb2e,0xba9ebb58,0xb8a8b9a8,0xb87fb9a8,0xb49fb710,0xb2f7b659,0x2884b01d,0x3109a7da,0x35b13257,0x38153570,
0xb602b832,0xb83ab972,0xaa7ab2ea,0xb185b5b6,0x347b2f72,0x32ad24b6,0x38a336f9,0x387a3642,0x3a8539a8,0x3aa239a8,0x3bae3b33,0x3bd33b5d,0x3bfd3bf2,0x3be13c00,0x3b6a3bd0,0x3acb3b79,
0x3b593ab5,0x3ab339ba,0x3bfc3bc7,0x3bdc3b6b,0x3bb33bf5,0x3bd73c00,0x3a893b39,0x3aa53b62,0x389e39a8,0x387439a8,0x345736e3,0x3263362b,0xac382eaa,0xb2011e48,0xb654b37d,0xb85fb5fd,
0xb99ab997,0xb89fb873,0xb99eb99c,0xb8f5b8ca,0xb9a3b9a0,0xb947b91e,0xb9a7b9a5,0xb995b96e,0xb9abb9a9,0xb9e0b9bb,0xb9b0b9ae,0xba26ba03,0xb9b4b9b2,0xba68ba48,0xb9b9b9b7,0xbaa6ba88,
0xb9d3b9d9,0xba9fbac0,0xb9c6b9cc,0xba59ba7d,0xb9b9b9bf,0xba0eba34,0xb9abb9b2,0xb9bdb9e6,0xb99eb9a5,0xb967b993,0xb991b997,0xb90db93b,0xb983b98a,0xb8aeb8de,0xb975b97c,0xb84cb87e,
0x395e3953,0x385c3824,0x3975396a,0x38c83892,0x398c3981,0x392f38fc,0x39a33997,0x39913961,0x39b939ae,0x39ec39bf,0x39cf39c4,0x3a423a18,0x39e439d9,0x3a913a6a,0x39f939ef,0x3ad93ab6,
0x3a0a3a18,0x3acb3af0,0x39ec39fb,0x3a7b3aa4,0x39cf39de,0x3a223a4f,0x39b039bf,0x39c139f3,0x399139a0,0x395a398e,0x39713981,0x38eb3923,0x39503961,0x387638b1,0x392f3940,0x37f63839,
0xb921b90b,0xb816b7a4,0xb94bb936,0xb89ab859,0xb975b961,0xb917b8d9,0xb99eb98a,0xb98cb953,0xb9c6b9b2,0xb9f9b9c4,0xb9ecb9d9,0xba5dba2c,0xba12b9ff,0xbab7ba8b,0xba36ba24,0xbb07bae1,
0xba3eba53,0xbaf5bb1d,0xba12ba28,0xba9bbaca,0xb9e4b9fb,0xba36ba6a,0xb9b4b9cc,0xb9c6b9ff,0xb983b99c,0xb94bb98a,0xb950b96a,0xb8c8b90b,0xb91cb936,0xb83cb883,0xb8e6b901,0xb750b7e6,
0x38e138c0,0x379e36fc,0x39213901,0x386b381e,0x395e3940,0x38fe38b6,0x399a397c,0x39883944,0x39d339b7,0x3a0539c8,0x3a0a39ef,0x3a773a40,0x3a3e3a24,0x3adc3aab,0x3a703a57,0x3b333b09,
0x3a703a8b,0x3b1c3b47,0x3a363a53,0x3abb3aed,0x39f93a18,0x3a4a3a84,0x39b939d9,0x39ca3a0c,0x39753997,0x393d3985,0x392f3953,0x38a438f2,0x38e6390b,0x38003854,0x389a38c0,0x36a73756,
0xb70db651,0xb4aeb309,0xb83cb7c5,0xb6ebb5d1,0xb8e6b892,0xb880b7fb,0xb983b936,0xb971b8fc,0xba12b9cc,0xba42b9de,0xba91ba53,0xbaefba9d,0xbafebaca,0xbb74bb37,0xbb5abb2e,0xbbcebba6,
0xbb40bb6c,0xbbb2bbd8,0xbad9bb0f,0xbb43bb80,0xba5dba9d,0xbaa6bafa,0xb9cfba18,0xb9e0ba48,0xb92fb981,0xb8f5b96e,0xb880b8d9,0xb7d5b873,0xb788b824,0xb590b6b8,0xb5fab6c3,0xb251b460,
0x367935a2,0x34113197,0x380b374b,0x3684354f,0x38cd386e,0x386637af,0x397e3928,0x396c38ed,0x3a1e39d1,0x3a4e39e2,0x3aa93a66,0x3b043aaf,0x3b1f3ae7,0x3b8c3b4e,0x3b7d3b51,0x3be03bbd,
0x3b613b8d,0x3bc73be8,0x3af53b2e,0x3b5a3b97,0x3a703ab6,0x3ab73b0f,0x39d33a24,0x39e43a53,0x3921397c,0x38e6396a,0x385c38c0,0x37883859,0x370d37e6,0x350e3651,0x3549362e,0x30de3383,
0xb5e2b4f0,0xb2e4b023,0xb7b4b6cf,0xb61db4cc,0xb8b4b849,0xb84cb761,0xb97ab919,0xb967b8de,0xba2ab9d5,0xba59b9e6,0xbac1ba79,0xbb19bac0,0xbb3dbb03,0xbba2bb65,0xbb9cbb70,0xbbefbbd0,
0xbb7fbbaa,0xbbd8bbf4,0xbb10bb4c,0xbb6fbbac,0xba82bacd,0xbac8bb23,0xb9d7ba30,0xb9e8ba5f,0xb912b978,0xb8d7b965,0xb836b8a7,0xb73ab83e,0xb690b783,0xb48ab5e8,0xb496b596,0xaecfb244,
0x3549343b,0x31a42d58,0x37503651,0x35b33447,0x389a3824,0x38313713,0x3975390b,0x396338cf,0x3a3639d9,0x3a6539ea,0x3ad93a8b,0x3b2d3ad0,0x3b5a3b1d,0x3bb53b7a,0x3bb73b8d,0x3bf93be0,
0x3b9a3bc3,0x3be73bfc,0x3b2a3b67,0x3b833bbe,0x3a943ae4,0x3ad93b37,0x39db3a3c,0x39ec3a6a,0x39033973,0x38c83961,0x3811388d,0x36eb3824,0x3611371e,0x3405357e,0x33c034fc,0x2bc03103,
0xb061a8cf,0x25b230ac,0xb549b383,0xb32eae84,0xb816b6c3,0xb750b57e,0xb95eb8c0,0xb94bb883,0xba70b9ef,0xba9bb9ff,0xbb40bae1,0xbb83bb1d,0xbbc7bb8d,0xbbf5bbcc,0xbbffbbed,0xbbeabbff,
0xbbf2bc00,0xbbfebbe3,0xbb96bbcf,0xbbd2bbf9,0xbae9bb49,0xbb25bb8b,0xb9f1ba75,0xba01baa1,0xb8b9b95c,0xb87bb949,0xb69bb809,0xb555b734,0xb2fdb514,0xad71b2bf,0xa376af7e,0x31662966,
0x2e39a052,0xabf2b21f,0x34de3276,0x32512c5e,0x37f63673,0x3718352c,0x395a38b1,0x39473873,0x3a7b39f3,0x3aa63a03,0x3b523af0,0x3b923b2c,0x3bd63b9f,0x3bfb3bd8,0x3c003bf6,0x3bda3bfc,
0x3bfa3bff,0x3bf93bd1,0x3ba73bdd,0x3bdd3bfd,0x3af83b5b,0x3b333b99,0x39f53a80,0x3a053aab,0x38a93957,0x386b3944,0x364b37db,0x350236fc,0x31ee34a8,0x2a9331e2,0xa8062cf4,0xb2d8ad3f,
0xab5c2af8,0x2e843390,0xb472b166,0xb172a86b,0xb7bfb622,0xb6e0b4d8,0xb955b8a2,0xb942b863,0xba86b9f7,0xbab0ba08,0xbb64bb00,0xbba0bb39,0xbbe3bbaf,0xbbffbbe2,0xbbfdbbfd,0xbbc6bbf5,
0xbbffbbfa,0xbbf1bbba,0xbbb7bbe8,0xbbe7bc00,0xbb07bb6c,0xbb40bba6,0xb9f9ba8b,0xba0abab6,0xb89ab953,0xb85cb940,0xb5fab7a4,0xb4aeb6c3,0xb0deb43b,0xa484b103,0x2cf4a8cf,0x34232fc9,
0x2484ae6b,0xb086b47e,0x34053055,0x30931248,0x378835d1,0x36a73484,0x39503892,0x393d3854,0x3a9139fb,0x3abb3a0c,0x3b743b0f,0x3bad3b47,0x3bed3bbe,0x3c003beb,0x3bf63c00,0x3bae3beb,
0x3c003bf0,0x3be53ba0,0x3bc53bf2,0x3bef3c00,0x3b163b7c,0x3b4d3bb3,0x39fd3a96,0x3a0e3ac0,0x388b394e,0x384c393b,0x35a8376c,0x345a368a,0x2f97339c,0xa4203023,0xafe298b6,0xb4d8b128,
0x31c93531,0x355b37e0,0xaf652839,0x9d7f315a,0xb66db42f,0xb584b1b0,0xb939b844,0xb925b803,0xbac5ba10,0xbaecba20,0xbbb9bb53,0xbbdfbb82,0xbbffbbf2,0xbbe3bc00,0xbb91bbde,0xbaf7bb8a,
0xbbd6bb81,0xbb7cbadf,0xbbf5bbfd,0xbc00bbdd,0xbb5abbbe,0xbb88bbe3,0xba12baca,0xba22baf0,0xb83cb936,0xb7f6b923,0xb405b651,0xb15ab567,0x2a61ae84,0x31e22052,0x358a3269,0x381935a8,
0xb309b5e2,0xb5f4b841,0x2da3ac44,0xa5b2b269,0x363433b4,0x35493103,0x39343834,0x392137e6,0x3acf3a14,0x3af53a24,0x3bc43b60,0x3be73b8d,0x3bfb3bf8,0x3bd63bff,0x3b703bce,0x3ac63b6d,
0x3bc53b5f,0x3b5d3aad,0x3bfa3bf9,0x3bff3bcf,0x3b663bc9,0x3b923bea,0x3a163ad4,0x3a263afa,0x382c3931,0x37d5391e,0x335f3617,0x30ac352c,0xad582cc2,0xb2f0a89d,0xb63ab3a8,0xb869b63f,
0x34233690,0x368a3890,0xabc02e6b,0x2a613377,0xb5fab309,0xb50eb055,0xb92fb824,0xb91cb7c5,0xbad9ba18,0xbafeba28,0xbbcebb6c,0xbbedbb97,0xbbf6bbfc,0xbbc7bbfd,0xbb4cbbba,0xba93bb4d,
0xbbafbb38,0xbb3cba77,0xbbfebbf2,0xbbfcbbbf,0xbb72bbd3,0xbb9cbbf0,0xba1abadd,0xba2abb03,0xb81cb92d,0xb7b4b919,0xb2b3b5dc,0xaffbb4f0,0x2f7ea9fd,0x33fd2c12,0x36e53472,0x38b636d4,
0xb4c0b73a,0xb71eb8dc,0x2839b048,0xacf4b441,0x35bf325d,0x34d22f4c,0x392a3813,0x391737a4,0x3ae23a1c,0x3b073a2c,0x3bd73b77,0x3bf33ba1,0x3bee3bff,0x3bb63bfa,0x3b233ba4,0x3a5b3b2a,
0x3b973b0d,0x3b183a3e,0x3c003be9,0x3bf73bad,0x3b7d3bdb,0x3ba63bf5,0x3a1e3ae7,0x3a2e3b0c,0x380b3928,0x37933914,0x320735a2,0x2e9d34b4,0xb0d124e9,0xb484add5,0xb78eb50e,0xb901b767,
0xb97239ba,0x39dc3996,0xb8323ab5,0x3ad0385d,0x3927b9fe,0xba1fb94d,0x37b7bae9,0xbb02b807,0xb8d83a3f,0x3a5e3900,0xb7053b1a,0x3b30375e,0x3887ba7c,0xba99b8b0,0x364ebb46,0xbb5ab6aa,
0xb90039dc,0x3a3f3972,0xad7e3be6,0x3bf83115,0x3807ba99,0xbae9b887,0xabd9bc00,0xbbfca248,0xb5f13b30,0x3b6e3705,0x32a13bed,0x3bd4b04e,0x3365bba0,0xbbc9b4d5,0xb593bbaf,0xbb803475,
0xb88739fe,0x3a99394d,0x35f13bbc,0x3b6eb414,0x3593bb1a,0xbb80b75e,0xb8b0bb02,0xba7c37b7,0xaf0e3bc9,0x3bf43365,0x3a1f39dc,0x3927b972,0xb04ebc00,0xbbed2248,0xbb30b85d,0xb7053ab5,
0xb8073a1f,0x3ae93927,0x39fe3a3f,0x394db900,0x31dbbb80,0xbbddb593,0xbb6eb832,0xb5f13ad0,0x31153c00,0x3be62248,0x3bff32a1,0x28b6bbd4,0xb7b7bb91,0xbb023534,0xbba0304e,0x34d53bed,
0xb7053a3f,0x3b303900,0x3bbc375e,0x3414bb1a,0x2248bbc9,0xbc00b365,0xbbdda8b6,0x31db3bff,0x36aa3bd4,0x3b46b2a1,0x3a7cb64e,0xb8b0bb5a,0xba1fba5e,0xb92738d8,0xb7b739fe,0x3b02394d,
0xb5f13a5e,0x3b6e38d8,0x3bd42bd9,0xb2a1bbfc,0xb115bbf4,0xbbe6af0e,0xb9dc375e,0x39723b1a,0x39273b46,0x3a1fb6aa,0x3475bad0,0xbbafb832,0xbb91b887,0xb5343a99,0x34143c00,0x3bbc2248,
0xb4d53a7c,0x3ba038b0,0x3a3fb593,0xb900bb80,0xb534bc00,0xbb912248,0xb4143ab5,0x3bbc385d,0x3a993a5e,0x3887b8d8,0xb5f1bbfc,0xbb6e2bd9,0xbbffb475,0x28b63baf,0x3ad03a1f,0x3832b927,
0xb3653a99,0x3bc93887,0x36aab996,0xbb46b9ba,0xb7b7bbed,0xbb02304e,0x34d53bfc,0x3ba02bd9,0x3b913927,0x3534ba1f,0xbae9ba3f,0xb8073900,0xbb5a28b6,0x364e3bff,0x3bd43115,0xb2a1bbe6,
0xb1153ab5,0x3be6385d,0xa8b6bb6e,0xbbffb5f1,0xb900bbbc,0xba3f3414,0x3a1f3b30,0x3927b705,0x3bfc375e,0x2bd9bb1a,0xbbedb475,0x304e3baf,0xb9ba3593,0x39963b80,0x3887b832,0xba99bad0,
0xad7e3ad0,0x3bf83832,0xb7b7bbff,0xbb0228b6,0xb9febb6e,0xb94d35f1,0x3bed3887,0x304eba99,0x3bd43414,0xb2a1bbbc,0xb9963534,0x39ba3b91,0xb6aa3900,0x3b463a3f,0xb115bba0,0xbbe6b4d5,
0xa2483ae9,0x3c003807,0xba99bb30,0xb8873705,0xbad0bb02,0xb83237b7,0x3b462d7e,0xb6aabbf8,0x3b1a28b6,0xb75ebbff,0xaf0e3a7c,0x3bf438b0,0xabd93ab5,0x3bfc385d,0xba5ebb5a,0xb8d8364e,
0x2bd93b02,0x3bfc37b7,0xbbedb927,0xb04e3a1f,0xbb6eba7c,0xb5f138b0,0x385db6aa,0xbab5bb46,0x39dcb1db,0xb972bbdd,0x38323c00,0x3ad02248,0x34d53bbc,0x3ba03414,0xbbf4b705,0x2f0e3b30,
0x304e3b1a,0x3bed375e,0xbb91b475,0x35343baf,0xbbd4b9dc,0xb2a13972,0x2248ba7c,0xbc00b8b0,0x3832b64e,0xbad0bb5a,0x3b803a99,0x3593b887,0x39003bfc,0x3a3fabd9,0xb9273414,0x3a1f3bbc,
0x32a13b30,0x3bd43705,0xb996304e,0x39ba3bed,0xbbffb927,0xa8b63a1f,0xb832bbf4,0xbad0af0e,0x3475b8b0,0xbbafba7c,0x3ba03593,0xb4d5bb80,0x3ae93b6e,0x3807b5f1,0x2bd93a99,0x3bfc3887,
0x34753b46,0x3baf36aa,0xb4d53832,0x3ba03ad0,0xbbedb85d,0x304e3ab5,0xbb30bb5a,0xb705364e,0x2248b9fe,0xbc00b94d,0x3887b414,0xba99bbbc,0x3be63a1f,0x3115b927,0x39dc3bf4,0x3972af0e,
0x35933b5a,0x3b80364e,0x31153a99,0x3be63887,0xbba0b705,0x34d53b30,0xbbf4b8d8,0x2f0e3a5e,0xb414bb02,0xbbbcb7b7,0xabd9ba1f,0xbbfcb927,0x3bd43832,0xb2a1bad0,0x3c003972,0xa248b9dc,
0x36aa3b6e,0x3b4635f1,0x38b03bdd,0x3a7c31db,0xbb1ab534,0x375e3b91,0xba3fb04e,0x39003bed,0xb807bbaf,0xbae9b475,0xb94dbbf8,0xb9fead7e,0x3ab53365,0xb85dbbc9,0x39ba28b6,0xb996bbff,
0x37b73b80,0x3b023593,0x3b1a3bc9,0x375eb365,0xba5eb2a1,0x38d83bd4,0xb53435f1,0x3b913b6e,0xb9babbfc,0xb996abd9,0xbbddbae9,0xb1db3807,0x38b0ad7e,0xba7cbbf8,0x28b6b900,0xbbffba3f,
0x385d3b91,0x3ab53534,0x3c003a5e,0x2248b8d8,0xb972ad7e,0x39dc3bf8,0x33653a3f,0x3bc93900,0xbb02bbe6,0xb7b73115,0xbb1ab6aa,0x375e3b46,0x3414b64e,0xbbbcbb5a,0xb94dbbdd,0xb9feb1db,
0x38d83ba0,0x3a5e34d5,0x3b3037b7,0xb705bb02,0xb85d28b6,0x3ab53bff,0x39ba3be6,0x39963115,0xbbc9bb6e,0xb36535f1,0xb6aa31db,0x3b463bdd,0xaf0eb94d,0xbbf4b9fe,0xbbf8bae9,0xad7e3807,
0x394d3baf,0x39fe3475,0x38d82d7e,0xba5ebbf8,0xb64e3115,0x3b5a3be6,0x3bd43b80,0x32a1b593,0xbbffba99,0x28b63887,0x336539ba,0x3bc93996,0xb75ebae9,0xbb1ab807,0xba3fb534,0x39003b91,
0x39ba3bbc,0x39963414,0x31dbb534,0xbbddbb91,0xb3653475,0x3bc93baf,0x3b803927,0xb593ba1f,0xbba0b972,0x34d539dc,0x3a3f3be6,0x39003115,0xb9febbd4,0xb94db2a1,0xb04e35f1,0x3bed3b6e,
0x3a1f3bc9,0x39273365,0xb475b972,0xbbafb9dc,0xabd9364e,0x3bfc3b5a,0x38d831db,0xba5ebbdd,0xbab5b807,0x385d3ae9,0x3c003b30,0x2248b705,0xbb80bbf4,0xb5932f0e,0x38b03b1a,0x3a7c375e,
0x3a7c3bd4,0x38b032a1,0xb972bb5a,0xb9dcb64e,0x2f0e3807,0x3bf43ae9,0x2d7eb534,0xbbf8bb91,0xb94db4d5,0x39fe3ba0,0x3a5e37b7,0xb8d8bb02,0xbc00bb46,0x224836aa,0x3bdd3bc9,0x31dbb365,
0x3ad03bdd,0x383231db,0xbb80bc00,0xb5932248,0x347538d8,0x3baf3a5e,0xb75eb9fe,0xbb1ab94d,0xb705ad7e,0x3b303bf8,0x3414af0e,0xbbbcbbf4,0xbb6eb9dc,0x35f13972,0x3ab538b0,0xb85dba7c,
0x3b1a3be6,0x375e3115,0xbbf4bb46,0x2f0e36aa,0x37053996,0x3b3039ba,0xbae9bbd4,0xb807b2a1,0xb1db304e,0x3bdd3bed,0xb64eb94d,0xbb5ab9fe,0xb9dcb7b7,0x39723b02,0x3365ad7e,0xbbc9bbf8,
0x3b5a3bed,0x364e304e,0xbab5b94d,0x385d39fe,0x38b03a3f,0x3a7c3900,0xbbffbba0,0x28b634d5,0x2d7e3593,0x3bf83b80,0xbb02bbc9,0xb7b7b365,0xb705b1db,0x3b303bdd,0xb807b9ba,0xbae9b996,
0x3b913bf4,0x35342f0e,0xb807b4d5,0x3ae93ba0,0x39ba3ad0,0x39963832,0xba99b972,0x388739dc,0x3593385d,0x3b803ab5,0xbbe6bb6e,0x311535f1,0xad7e304e,0x3bf83bed,0xbbafbbfc,0xb475abd9,
0x3bbc3bf8,0x34142d7e,0xabd92f0e,0x3bfc3bf4,0x3a993b46,0x388736aa,0xb64eb365,0x3b5a3bc9,0x38b039ba,0x3a7c3996,0xb972b85d,0x39dc3ab5,0x34753705,0x3baf3b30,0xbb1aba5e,0x375e38d8,
0x3bdd3bfc,0x31db2bd9,0x364e3807,0x3b5a3ae9,0x3b463ba0,0x36aa34d5,0x31153475,0x3be63baf,0x3a3f3ad0,0x39003832,0xad7e28b6,0x3bf83bff,0x38d83996,0x3a5e39ba,0xb534b2a1,0x3b913bd4,
0x3bf43bff,0x2f0e28b6,0x3a1f3a7c,0x392738b0,0x3bbc3bdd,0x341431db,0x394d39ba,0x39fe3996,0x3b5a3b91,0x364e3534,0x385d38d8,0x3ab53a5e,0x3ad03b1a,0x3832375e,0x36aa37b7,0x3b463b02,
0x3bff3c00,0x28b62248,0x3bc93bd4,0x336532a1,0x3bf83bfc,0x2d7e2bd9,0x3baf3bbc,0x34753414,0x3bed3bf4,0x304e2f0e,0x3b913ba0,0x353434d5,0x3bdd3be6,0x31db3115,0x3b6e3b80,0x35f13593,
0xb5933b6e,0x3b8035f1,0xb1153bdd,0x3be631db,0x34d5bb91,0xbba0b534,0x2f0ebbed,0xbbf4b04e,0xb4143baf,0x3bbc3475,0xabd93bf8,0x3bfc2d7e,0x32a1bbc9,0xbbd4b365,0x2248bbff,0xbc00a8b6,
0x37b73b46,0x3b02b6aa,0x3b1a3832,0x375ebad0,0xb8d8bab5,0xba5e385d,0xbb91b64e,0xb5343b5a,0x39ba39fe,0x3996b94d,0x3bdd3414,0x31dbbbbc,0xba7cb927,0xb8b03a1f,0xbbffaf0e,0xa8b63bf4,
0x3bd43534,0x32a1bb91,0x39bab8d8,0xb996ba5e,0xbbffad7e,0x28b63bf8,0xb8323a3f,0x3ad03900,0x3bafb115,0xb475bbe6,0x34d5bb46,0xbba0b6aa,0xbae9364e,0x38073b5a,0xabd93bdd,0x3bfc31db,
0x3a5eb75e,0xb8d8bb1a,0xb705bbaf,0xbb303475,0xb85d39dc,0x3ab53972,0x39ba3a7c,0x3996b8b0,0x3365bb5a,0xbbc9b64e,0xbb46b887,0xb6aa3a99,0x2f0e3bfc,0x3bf42bd9,0x3bf83414,0x2d7ebbbc,
0x2bd9bbaf,0xbbfcb475,0xbbedad7e,0x304e3bf8,0x35f13be6,0x3b6eb115,0x3ab5b593,0xb85dbb80,0xb9dcba99,0xb9723887,0xb83239ba,0x3ad03996,0x3ba03807,0x34d5bae9,0x2f0ebb91,0xbbf4b534,
0xb9babae9,0xb9963807,0xb1db3b30,0x3bdd3705,0x3bc937b7,0x3365bb02,0xb593bbf8,0xbb802d7e,0xbba028b6,0x34d53bff,0x3a3f3a7c,0x3900b8b0,0x394db85d,0xb9febab5,0xbbedb64e,0xb04e3b5a,
0xbbf8b365,0x2d7e3bc9,0x3b0239dc,0x37b7b972,0x39feb64e,0xb94dbb5a,0xbbedb1db,0x304e3bdd,0xb2a13ae9,0x3bd43807,0x39bab705,0xb996bb30,0xb6aabbf4,0xbb462f0e,0xb1153b1a,0x3be6375e,
0xb8b0385d,0x3a7c3ab5,0x39dcb5f1,0xb972bb6e,0xaf0ebbbc,0xbbf4b414,0xad7e3b30,0x3bf83705,0x39fe3b1a,0x394db75e,0xb8d8bbaf,0xba5e3475,0xbc00b593,0x22483b80,0x3bdd3832,0x31dbbad0,
0x33653bdd,0x3bc931db,0xb6aabc00,0xbb462248,0xbb02ba5e,0xb7b738d8,0x3ba0394d,0x34d5b9fe,0x3b912d7e,0xb534bbf8,0xbae92f0e,0x38073bf4,0xb64e3972,0x3b5a39dc,0x32a1ba7c,0xbbd4b8b0,
0x3b1a3a7c,0x375eb8b0,0xbbf4b593,0x2f0e3b80,0xbb30a248,0x37053c00,0x3807b85d,0xbae9bab5,0x31dbba5e,0xbbddb8d8,0x364e3bfc,0x3b5a2bd9,0x39723baf,0x39dcb475,0xbbc9b927,0xb3653a1f,
0x3b6e304e,0xb5f1bbed,0xb2a139fe,0x3bd4394d,0xb1153a3f,0x3be63900,0xb9dcbba0,0xb97234d5,0xba1fbb80,0xb9273593,0x3baf3365,0xb475bbc9,0x3b9131db,0xb534bbdd,0xb41439ba,0x3bbc3996,
0x3534b900,0xbb91ba3f,0x3ae93b1a,0x3807b75e,0x39ba3bc9,0x3996b365,0xba9928b6,0x38873bff,0xbb80b2a1,0x35933bd4,0xb115bb5a,0xbbe6b64e,0x2d7eba5e,0xbbf8b8d8,0x3baf39fe,0x3475b94d,
0xb807bbf8,0xbae9ad7e,0x39feaf0e,0xb94dbbf4,0x3bdd36aa,0xb1dbbb46,0x35f13bc9,0x3b6e3365,0xb11539ba,0x3be63996,0xbbffb85d,0x28b63ab5,0xbb02bb30,0xb7b73705,0x34d5b8d8,0xbba0ba5e,
0xbbddb9fe,0xb1db394d,0xb64ebbbc,0xbb5ab414,0x36aab75e,0xbb46bb1a,0x3be637b7,0xb115bb02,0x3a3f3bc9,0x3900b365,0xad7e39dc,0x3bf83972,0xba5ea248,0x38d83c00,0xbb91bab5,0xb534385d,
0xba3fa8b6,0x39003bff,0xbbf8b8b0,0x2d7e3a7c,0xb807bbdd,0xbae9b1db,0x2bd9b9ba,0xbbfcb996,0x3b6e3534,0xb5f1bb91,0x3bd43a5e,0x32a1b8d8,0x33653b1a,0x3bc9375e,0xb59337b7,0x3b803b02,
0xa8b63996,0x3bff39ba,0xb365385d,0x3bc93ab5,0xbbf8b9fe,0xad7e394d,0xbbafbae9,0xb4753807,0x304eb900,0xbbedba3f,0x3534b75e,0xbb91bb1a,0x3bdd3a7c,0x31dbb8b0,0x3b6e3b46,0x35f1b6aa,
0x39dc3c00,0x3972a248,0x3ad03bd4,0x3832b2a1,0xb9272bd9,0x3a1f3bfc,0xb7b73414,0x3b023bbc,0xba5ebbf4,0xb8d82f0e,0xbb30bba0,0xb70534d5,0x3887b115,0xba99bbe6,0x364eb593,0xbb5abb80,
0x3bf43972,0xaf0eb9dc,0x3a1f3115,0xb927bbe6,0x34143a99,0x3bbc3887,0x39fe3c00,0x394d2248,0xbb5ab705,0x364e3b30,0xb85d304e,0x3ab53bed,0xb832bba0,0xbad0b4d5,0xbb46bbaf,0xb6aa3475,
0x3887abd9,0xba99bbfc,0xb5f1bae9,0xbb6eb807,0x3b803ba0,0x3593b4d5,0x3a7c3475,0xb8b0bbaf,0xaf0e3832,0x3bf43ad0,0x3a1f3bff,0x392728b6,0xbbedb996,0x304e39ba,0xb70532a1,0x3b303bd4,
0xb414ba1f,0xbbbcb927,0xbbfcba3f,0x2bd93900,0x3a993593,0xb887bb80,0xb64ebad0,0xbb5ab832,0x3a7c3c00,0x38b02248,0x39dc32a1,0xb972bbd4,0xb4753534,0x3baf3b91,0x3b1a3bed,0x375eb04e,
0xbb30bbf4,0xb7052f0e,0xb41434d5,0x3bbc3ba0,0x2248b832,0xbc00bad0,0xbbddb9dc,0x31db3972,0x3b46385d,0xb6aabab5,0xb8b0bb6e,0xba7cb5f1,0x3a1f3bed,0x3927304e,0x37b7abd9,0xbb02bbfc,
0xbb5ab8d8,0x364e3a5e,0x3ab53bfc,0x385d2bd9,0xba7cbbf4,0xb8b0af0e,0xa8b6375e,0x3bff3b1a,0x2d7eb6aa,0xbbf8bb46,0xbb02b832,0x37b73ad0,0x3b303887,0xb705ba99,0xbae9bc00,0xb807a248,
0xb4d53115,0x3ba03be6,0x3a3f36aa,0xb900bb46,0xbb91b996,0x353439ba,0x3bbc3bd4,0x3414b2a1,0xba99bbed,0xb887b04e,0x35f139fe,0x3b6e394d,0xa8b6b7b7,0xbbffbb02,0xb832ad7e,0x3ad03bf8,
0x38323a99,0x3ad03887,0xb593b996,0xbb80b9ba,0xb475304e,0x3baf3bed,0x375e2bd9,0xbb1abbfc,0xbb30b927,0x37053a1f,0x3bbc3a3f,0xb414b900,0xbb6ebbff,0xb5f128b6,0x3ab53be6,0x385d3115,
0x3be63bd4,0x3115b2a1,0xbbffbb5a,0x28b6364e,0x39003ae9,0x3a3f3807,0xba1fbb91,0xb927b534,0xabd934d5,0x3bfc3ba0,0xb04eb7b7,0xbbedbb02,0xb9bab6aa,0x39963b46,0x38873365,0xba99bbc9,
0x3a1f3832,0xb927bad0,0xb47528b6,0x3baf3bff,0x3bfc3b6e,0xabd9b5f1,0xba5eb887,0x38d83a99,0x3ab53bbc,0x385d3414,0xbc00bb91,0x22483534,0x35933900,0x3b803a3f,0xba7cbba0,0xb8b0b4d5,
0x2248b414,0xbc00bbbc,0x3a993b91,0x38873534,0x38323475,0xbad0bbaf,0x36aa3927,0x3b463a1f,0x3b1a39dc,0xb75eb972,0xaf0e3115,0x3bf43be6,0x3bfc3bd4,0x2bd9b2a1,0xb8d8b5f1,0x3a5e3b6e,
0xb9febb02,0xb94db7b7,0x3a5e3927,0xb8d8ba1f,0xb64eb8b0,0xbb5aba7c,0x3bd43b46,0xb2a1b6aa,0x28b6b1db,0xbbffbbdd,0x3bc93c00,0x33652248,0x375e3414,0xbb1abbbc,0x3a3f3b30,0x39003705,
0xbbedbba0,0x304e34d5,0xb534b7b7,0xbb91bb02,0xbbd4bbff,0xb2a1a8b6,0x2248b115,0xbc00bbe6,0xbad0bb6e,0xb832b5f1,0x359331db,0xbb80bbdd,0xb900b9fe,0xba3fb94d,0x39273807,0xba1fbae9,
0xb85db705,0x3ab53b30,0xbc00bbed,0x2248304e,0xb9dcb927,0x39723a1f,0xbbc9bbf4,0xb365af0e,0xbb02ba7c,0x37b738b0,0xbb1abb80,0xb75eb593,0xbbbcbb6e,0x341435f1,0xb9feba99,0xb94db887,
0x34753593,0x3baf3b80,0xb4d5b365,0x3ba03bc9,0x304e32a1,0x3bed3bd4,0xb705b5f1,0x3b303b6e,0xa2482bd9,0x3c003bfc,0xb887b807,0x3a993ae9,0xb115ad7e,0x3be63bf8,0xb972b900,0x39dc3a3f,
0x3b463b5a,0x36aa364e,0x3a7c3a99,0x38b03887,0x3b1a3b30,0x375e3705,0x3a3f3a5e,0x390038d8,0x3ae93b02,0x380737b7,0x39fe3a1f,0x394d3927,0x3ab53ad0,0x385d3832,0x39ba39dc,0x39963972,
0x28b63c00,0x3bffa248,0x33653bd4,0x3bc9b2a1,0xad7ebbfc,0xbbf82bd9,0xb475bbbc,0xbbaf3414,0x304e3bf4,0x3bedaf0e,0x35343ba0,0x3b91b4d5,0xb1dbbbe6,0xbbdd3115,0xb5f1bb80,0xbb6e3593,
0x3bf4a8b6,0xaf0ebbff,0x3a1fb8b0,0xb927ba7c,0xbbbc31db,0x34143bdd,0xb94d3996,0x39fe39ba,0x3b5ab534,0xb64ebb91,0x385dba5e,0xbab5b8d8,0xbad0375e,0x38323b1a,0xb6aa3b02,0x3b4637b7,
0xb1dbbbfc,0xbbdd2bd9,0xbb5ab807,0xb64e3ae9,0x36aa3ba0,0x3b46b4d5,0x3be63475,0x3115bbaf,0xb900bad0,0xba3f3832,0xbbf8a8b6,0x2d7e3bff,0x3a5e3996,0x38d8b9ba,0x3b91b2a1,0xb534bbd4,
0xbbbc2d7e,0x34143bf8,0x2bd93bf4,0x3bfc2f0e,0x3a99b6aa,0xb887bb46,0xb64ebbc9,0xbb5a3365,0xb8b03996,0x3a7c39ba,0x39723ab5,0x39dcb85d,0x3475bb30,0xbbafb705,0xbb1ab8d8,0xb75e3a5e,
0x35343bf4,0x3b91af0e,0x3ae9b4d5,0xb807bba0,0xb996bad0,0xb9ba3832,0xb8873972,0x3a9939dc,0x3b80385d,0x3593bab5,0x3115bb6e,0xbbe6b5f1,0xbbf8b04e,0x2d7e3bed,0x34753bfc,0x3bafabd9,
0x3b5ab04e,0xb64ebbed,0xbab5b9fe,0xb85d394d,0xb8b03900,0x3a7c3a3f,0x3bff34d5,0x28b6bba0,0x2d7ebb80,0xbbf8b593,0xbb023365,0x37b73bc9,0x37053bdd,0x3b30b1db,0x3807b996,0xbae9b9ba,
0xb75ebbe6,0xbb1a3115,0xaf0e3b46,0x3bf436aa,0x3b303996,0x3705b9ba,0xb807bbd4,0xbae932a1,0xbbddb04e,0x31db3bed,0x3b5a394d,0x364eb9fe,0x3972b7b7,0xb9dcbb02,0xbbc9ad7e,0x33653bf8,
0xbad031db,0x38323bdd,0x3b802248,0xb593bc00,0x3475ba5e,0xbbafb8d8,0xb75e394d,0x3b1a39fe,0x37053bf8,0x3b30ad7e,0xb414bbf4,0xbbbcaf0e,0xbb6eb972,0xb5f139dc,0x3ab53a7c,0x385db8b0,
0x38b03bd4,0x3a7cb2a1,0xb9dcbb5a,0xb972364e,0xbbf4b807,0xaf0e3ae9,0x3bf83534,0xad7ebb91,0x39feb4d5,0xb94dbba0,0xb8d837b7,0x3a5e3b02,0xa2483b46,0x3c0036aa,0xb1dbbbc9,0xbbddb365,
0x3a1fb365,0xb927bbc9,0xb47539dc,0x3baf3972,0x2bd93b5a,0x3bfc364e,0xb8d8bbdd,0xba5e31db,0xbab5bae9,0xb85d3807,0x3c003705,0xa248bb30,0x3b802f0e,0xb593bbf4,0xb8b0375e,0x3a7c3b1a,
0xb996bbbc,0xb9ba3414,0x3bdd3534,0xb1dbbb91,0x3bc93475,0xb365bbaf,0xb5933927,0x3b803a1f,0xb4d53972,0x3ba039dc,0xb900bbe6,0xba3f3115,0xb94dbbd4,0xb9fe32a1,0x3bed35f1,0xb04ebb6e,
0xb94d3475,0x39fe3baf,0xb8d8bbf8,0xba5e2d7e,0xb64ebbe6,0xbb5ab115,0x3bd43593,0xb2a1bb80,0x3bff3887,0x28b6ba99,0xb3653996,0x3bc939ba,0xb75e3807,0x3b1a3ae9,0xba3fbb91,0xb9003534,
0x3a5e3ba0,0x38d8b4d5,0xb70537b7,0x3b303b02,0xbab5a8b6,0x385d3bff,0xb996bbe6,0xb9ba3115,0xb365bb6e,0xbbc9b5f1,0x3b4631db,0xb6aabbdd,0x3bf4394d,0x2f0eb9fe,0x2d7e3ae9,0x3bf83807,
0x385db534,0xbab5bb91,0x3c0038d8,0xa248ba5e,0x39723bf8,0x39dcad7e,0xb3653900,0x3bc93a3f,0xbb02b115,0x37b73be6,0xbb1abb46,0xb75e36aa,0xb414bb5a,0xbbbcb64e,0x394db1db,0xb9febbdd,
0xbb02bb80,0xb7b73593,0xb75ebbc9,0xbb1ab365,0x38d8b2a1,0xba5ebbd4,0x3b9135f1,0xb534bb6e,0x39963bfc,0x39baabd9,0x31db3ae9,0x3bdd3807,0xba7cad7e,0x38b03bf8,0xbbffb900,0x28b63a3f,
0xb6aa35f1,0x3b463b6e,0xb8b031db,0x3a7c3bdd,0xbb1abb91,0xb75e3534,0xba3fbbed,0xb900304e,0x3807b475,0xbae9bbaf,0x394dad7e,0xb9febbf8,0x3ab53bc9,0x385db365,0x39ba3bff,0x3996a8b6,
0x3b803b5a,0x3593b64e,0x3be63a99,0x3115b887,0xb4d53705,0x3ba03b30,0xaf0e38d8,0x3bf43a5e,0xbbbcbb02,0xb41437b7,0xbbfcba1f,0xabd93927,0x32a1b832,0xbbd4bad0,0x2248b972,0xbc00b9dc,
0x3475b6aa,0xbbafbb46,0xb4d5bad0,0xbba0b832,0x3bed3ab5,0x304eb85d,0x3b30364e,0xb705bb5a,0x2248394d,0x3c0039fe,0x38873bbc,0x3a993414,0xbbe6b927,0x31153a1f,0xb9dcaf0e,0x39723bf4,
0xbbd4bb30,0xb2a13705,0xb9bab04e,0x39963bed,0xa8b6b927,0xbbffba1f,0xbad0bbf4,0xb8322f0e,0x3baf38b0,0xb475ba7c,0x34d5b593,0xbba0bb80,0x38073b6e,0x3ae935f1,0x3bfc3a99,0x2bd9b887,
0xb04e375e,0x3bed3b1a,0x3b913baf,0x3534b475,0xbbd4b972,0x32a139dc,0x224838b0,0x3c003a7c,0xb832bb5a,0xbad0b64e,0xbb80b887,0x35933a99,0x39002bd9,0xba3fbbfc,0xb927bbbc,0xba1fb414,
0x3bfc3b02,0x2bd9b7b7,0xb04eb927,0xbbedba1f,0x35f13a7c,0x3b6e38b0,0x3ab536aa,0xb85dbb46,0xb972b1db,0x39dc3bdd,0x3ad03c00,0x3832a248,0xbba0bbbc,0xb4d53414,0xaf0e3705,0x3bf43b30,
0xa248b807,0xbc00bae9,0xba99b705,0x38873b30,0x3ad037b7,0xb832bb02,0xbb46bbf8,0xb6aa2d7e,0x3b1a3bff,0x375ea8b6,0xaf0eb8b0,0xbbf4ba7c,0x2bd9385d,0x3bfc3ab5,0x3a5e364e,0xb8d8bb5a,
0xbbf8bad0,0x2d7e3832,0x3b023bff,0x37b728b6,0xb94dbb6e,0xb9feb5f1,0x304e3887,0x3bed3a99,0x32a1b414,0xbbd4bbbc,0xb9bab534,0x39963b91,0x3b463900,0xb6aaba3f,0xbbe6bba0,0xb11534d5,
0x3115385d,0x3be63ab5,0x28b6b5f1,0xbbffbb6e,0xb900b414,0x3a3f3bbc,0x3a1f3705,0xb927bb30,0xbbfcbb1a,0x2bd9375e,0x3bed3baf,0x304eb475,0xb9babb80,0xb996b593,0x38873ad0,0x3a993832,
0x3bc93a99,0xb365b887,0xbb46b996,0x36aa39ba,0x3b023bed,0x37b7304e,0xbba0bbfc,0xb4d52bd9,0x35343927,0x3b913a1f,0xb807ba3f,0xbae9b900,0xb64ea8b6,0x3b5a3bff,0x32a1b115,0xbbd4bbe6,
0xb4d5b8b0,0xbba0ba7c,0x3a3f3b80,0x39003593,0x35342248,0xbb91bc00,0x3414385d,0x3bbc3ab5,0x3a9938d8,0xb887ba5e,0xb5f1abd9,0x3b6e3bfc,0x3bff3baf,0x28b6b475,0xbad0b927,0x38323a1f,
0xbb6eba5e,0x35f138d8,0x32a1abd9,0xbbd4bbfc,0xbbe6bbf4,0xb1152f0e,0x3972375e,0xb9dcbb1a,0xba1fbb46,0xb927b6aa,0x3baf3ad0,0xb475b832,0xb534b887,0xbb91ba99,0x3bbc3c00,0x3414a248,
0x37053900,0x3b303a3f,0xbbbcbb1a,0x3414375e,0x22483365,0x3c003bc9,0xbbddbbff,0xb1db28b6,0xb6aab2a1,0x3b463bd4,0xba7cbb5a,0xb8b0b64e,0xba1fb8d8,0x39273a5e,0xb7b7b94d,0xbb02b9fe,
0x3ae93a1f,0xb807b927,0x394d3a3f,0x39fe3900,0x3bdd3b80,0xb1dbb593,0x35f13832,0x3b6e3ad0,0x3be63c00,0x3115a248,0x28b632a1,0x3bff3bd4,0x3b023b91,0x37b73534,0xb4d5b04e,0x3ba03bed,
0xb887b94d,0xba99b9fe,0x35f13414,0xbb6ebbbc,0xb593b75e,0xbb80bb1a,0x38b037b7,0xba7cbb02,0xaf0eb365,0xbbf4bbc9,0x3a1f3972,0xb927b9dc,0x304e2248,0xbbedbc00,0x3b303ab5,0xb705b85d,
0xba3fb9dc,0x39003972,0xbbf8bbe6,0x2d7e3115,0xbae9ba99,0x38073887,0xbbfcbc00,0xabd92248,0xbb6ebb30,0x35f13705,0xbbd4bbed,0xb2a1b04e,0xbbc9bba0,0x336534d5,0xbb80bbaf,0xb593b475,
0x39723996,0x39dc39ba,0x3832385d,0x3ad03ab5,0x3927394d,0x3a1f39fe,0x37b73807,0x3b023ae9,0x38d83900,0x3a5e3a3f,0x3705375e,0x3b303b1a,0x388738b0,0x3a993a7c,0x364e36aa,0x3b5a3b46,
0x36aa3b5a,0x3b46b64e,0x38b03a99,0x3a7cb887,0xb75ebb30,0xbb1a3705,0xb900ba5e,0xba3f38d8,0x38073b02,0x3ae9b7b7,0x394d3a1f,0x39feb927,0xb85dbad0,0xbab53832,0xb996b9dc,0xb9ba3972,
0x3475bb80,0xbbafb593,0xb4d5bbc9,0xbba03365,0xb04e3bd4,0x3bed32a1,0x37053b6e,0x3b30b5f1,0xa248bbfc,0xbc00abd9,0xb887bae9,0xba993807,0x31153bf8,0x3be6ad7e,0x39723a3f,0x39dcb900,
0xbab53705,0x385d3b30,0xa2483bed,0x3c00304e,0x3972b927,0xb9dcba1f,0xb365bbf4,0xbbc92f0e,0xb7b73a7c,0x3b0238b0,0x375e3b80,0x3b1ab593,0x3414bb6e,0xbbbcb5f1,0xb94dba99,0xb9fe3887,
0x3bed34d5,0x304ebba0,0x3534bb02,0xbb91b7b7,0xbbd428b6,0x32a13bff,0x22483be6,0x3c003115,0x3ad0b5f1,0xb832bb6e,0xb593bbdd,0xbb8031db,0xb900394d,0x3a3f39fe,0x39273ae9,0x3a1fb807,
0xb94dbb02,0xb9fe37b7,0xb8d83927,0x3a5e3a1f,0x3b5a38b0,0x364eba7c,0x32a1bb46,0xbbd4b6aa,0xbbffb1db,0x28b63bdd,0x33653c00,0x3bc9a248,0x3b1ab414,0xb75ebbbc,0xb900bb30,0xba3f3705,
0x22483bbc,0x3c003414,0x3a99b534,0xb887bb91,0xb832bbaf,0xbad03475,0xb6aa3a1f,0x3b463927,0x3b1a3972,0x375eb9dc,0xaf0ebbe6,0xbbf4b115,0xbbfcb2a1,0x2bd93bd4,0x38d83b6e,0x3a5eb5f1,
0x3927b832,0xba1fbad0,0xbbafa8b6,0x34753bff,0xabd93b6e,0x3bfc35f1,0x38d8b887,0xba5eba99,0xb85dbbbc,0xbab53414,0xa2483b91,0x3c003534,0x3b803900,0x3593ba3f,0xb8b0bba0,0xba7c34d5,
0xbbe6b2a1,0x31153bd4,0x3bff364e,0x28b6bb5a,0x3900b807,0xba3fbae9,0xba1f3534,0x39273b91,0x2bd93ba0,0x3bfc34d5,0x304ebb02,0xbbedb7b7,0xb9babb46,0xb99636aa,0x38873bc9,0x3a99b365,
0x3ad03a99,0x3832b887,0xbb80b996,0xb59339ba,0xbbafb04e,0x34753bed,0x3b1aabd9,0xb75ebbfc,0x3705b927,0xbb30ba1f,0xb4143a3f,0x3bbc3900,0x35f13bff,0x3b6e28b6,0xb85dbbe6,0xbab53115,
0xb4d5bbe6,0xbba0b115,0x3a3f3b46,0x3900b6aa,0x3b9139ba,0x3534b996,0xbbbcb2a1,0x34143bd4,0xba99304e,0x38873bed,0x35f1b94d,0xbb6eb9fe,0x28b6bb02,0xbbffb7b7,0x38323bf8,0x3ad0ad7e,
0xb64e38d8,0x3b5a3a5e,0xb85dbbfc,0xbab52bd9,0xb8b0bbf4,0xba7c2f0e,0x3bff375e,0xa8b6bb1a,0x3bf836aa,0xad7ebb46,0xb7b73832,0x3b023ad0,0xb7053887,0x3b303a99,0xb807bc00,0xbae92248,
0x3b302f0e,0xb705bbf4,0x34143ba0,0x3bbc34d5,0x22483ad0,0x3c003832,0xbbddb972,0xb1db39dc,0xbb46bab5,0xb6aa385d,0x38b0b5f1,0xba7cbb6e,0x3a1fb04e,0xb927bbed,0x37b73bfc,0x3b022bd9,
0xbbbcba1f,0xb4143927,0x2bd9ba3f,0xbbfcb900,0x3887b593,0xba99bb80,0x3b5a3ad0,0x364eb832,0x38b03c00,0x3a7ca248,0xb97232a1,0x39dc3bd4,0xbbafb534,0x34753b91,0xb75ebbed,0xbb1ab04e,
0x38873bfc,0x3a992bd9,0xb5f13807,0x3b6e3ae9,0xbb80b4d5,0x35933ba0,0xba7cbbaf,0xb8b03475,0xaf0ebad0,0xbbf4b832,0x3a1fa8b6,0xb927bbff,0x3bed39ba,0x304eb996,0x37053bd4,0x3b3032a1,
0x2f0eb972,0xbbf4b9dc,0x3927b115,0xba1fbbe6,0x3bbc3a99,0x3414b887,0x394d3c00,0x39fea248,0xb64e3705,0x3b5a3b30,0xbab5b04e,0x385d3bed,0xbad0bba0,0xb83234d5,0xb6aabbaf,0xbb46b475,
0xb9dca248,0x39723c00,0xbad0b2a1,0x38323bd4,0xb927bbfc,0xba1fabd9,0xb7b7bbbc,0xbb02b414,0x3a5e2f0e,0xb8d8bbf4,0x3b3034d5,0xb705bba0,0x38873be6,0x3a993115,0x364e3b80,0x3b5a3593,
0x3bff3996,0xa8b6b9ba,0x3bc9385d,0xb365bab5,0x2d7e39fe,0x3bf8394d,0x34753ae9,0x3baf3807,0xbbedb900,0x304e3a3f,0xbb91b75e,0x35343b1a,0xb1dbba7c,0xbbddb8b0,0xb5f1bb46,0xbb6eb6aa,
0xba3fbbff,0xb90028b6,0xbbf8ba7c,0xad7e38b0,0x3807b1db,0xbae9bbdd,0xabd9b996,0xbbfcb9ba,0x3b6e3b91,0x35f1b534,0x3bd438d8,0xb2a1ba5e,0xb365375e,0x3bc93b1a,0x35933b02,0x3b8037b7,
0x31db39fe,0x3bdd394d,0x3b5a3bbc,0x364eb414,0xbb46b75e,0x36aa3b1a,0xb11537b7,0x3be63b02,0xb900bbc9,0xba3fb365,0xbbf8b9dc,0x2d7e3972,0x38d8a248,0xba5ebc00,0xb534bab5,0xbb91b85d,
0x3807ad7e,0xbae9bbf8,0xb9febbf4,0xb94daf0e,0x3bdd3b46,0x31dbb6aa,0x35f1b365,0xbb6ebbc9,0x31153996,0x3be639ba,0x3bff3ab5,0x28b6b85d,0xbb02b705,0x37b73b30,0x34d53a5e,0x3ba038d8,
0xbb91b900,0x35343a3f,0x38073b1a,0x3ae9375e,0xb996bbc9,0xb9bab365,0xb887a8b6,0x3a993bff,0x3593b2a1,0xbb80bbd4,0xbbe6bb5a,0xb115364e,0x3bf83a5e,0xad7eb8d8,0xb475b9fe,0xbbafb94d,
0x3b6e3bed,0x35f1b04e,0xb2a1b94d,0xbbd4b9fe,0x31153900,0x3be63a3f,0x39dc34d5,0xb972bba0,0xba1fb593,0x39273b80,0x3baf3bc9,0x3475b365,0xbb91bbdd,0xb53431db,0x34143996,0x3bbc39ba,
0xb75eba7c,0xbb1ab8b0,0xaf0e3593,0x3bf43b80,0x3705a248,0xbb30bc00,0xbae9b85d,0x38073ab5,0x3bdd3a5e,0xb1dbb8d8,0xbb5abbfc,0xb64e2bd9,0x39dc3baf,0x39723475,0xb365b927,0xbbc9ba1f,
0xb36531db,0x3bc93bdd,0x36aa2248,0xbb46bc00,0xbb02b8d8,0x37b73a5e,0x3ba039fe,0xb4d5b94d,0xbb91bbf8,0xb5342d7e,0x3ae93bf4,0x38072f0e,0xb64eb9dc,0xbb5ab972,0x32a138b0,0x3bd43a7c,
0x3a7c385d,0xb8b0bab5,0xb972b5f1,0x39dc3b6e,0x3bf43bbc,0x2f0eb414,0xbbf8bb30,0x2d7e3705,0x394d3b1a,0x39fe375e,0xba5ebbaf,0xb8d8b475,0xa2483593,0x3c003b80,0xb1dbb832,0xbbddbad0,
0xbbf8bbc9,0xad7e3365,0x3b023972,0xb7b7b9dc,0xb9febb5a,0xb94db64e,0x3bed3bdd,0x304eb1db,0xb2a1b807,0xbbd4bae9,0x39ba3b30,0x39963705,0x36aa2f0e,0xbb46bbf4,0x3115375e,0x3be63b1a,
0x39963ae9,0x39ba3807,0xbbddbb30,0x31db3705,0x336537b7,0x3bc93b02,0xbb80bbf8,0xb593ad7e,0xb4d5a8b6,0x3ba03bff,0xb900ba7c,0xba3fb8b0,0xb9feb85d,0x394d3ab5,0xb04eb64e,0xbbedbb5a,
0xabd9b475,0xbbfcbbaf,0x3bed3bf8,0x304ead7e,0x35f13115,0xbb6ebbe6,0x3ab53b80,0x385d3593,0x39dc3887,0xb972ba99,0x38323996,0x3ad039ba,0x3ba03ae9,0xb4d5b807,0x2f0e3534,0x3bf43b91,
0xb8d8b75e,0x3a5e3b1a,0xbb30bbaf,0xb705b475,0xbab5b9dc,0x385d3972,0xb996ba7c,0xb9bab8b0,0xbbc9bb5a,0x3365364e,0xb6aab887,0xbb46ba99,0xbbf4bbfc,0xaf0e2bd9,0xad7eb414,0xbbf8bbbc,
0x3bd43b91,0xb2a1b534,0x39ba3a5e,0x399638d8,0x3bff3bf8,0x28b6ad7e,0x38323900,0x3ad03a3f,0x3baf3be6,0x34753115,0x34d536aa,0x3ba03b46,0x3ae93b5a,0x3807364e,0x2bd931db,0x3bfc3bdd,
0xbb02bb46,0xb7b7b6aa,0xb75eb832,0xbb1abad0,0xba5ebab5,0xb8d8b85d,0xb534b64e,0xbb91bb5a,0xb996b9fe,0xb9bab94d,0xb1dbb414,0xbbddbbbc,0xb8b0b927,0xba7cba1f,0xa8b6af0e,0xbbffbbf4,
0x359335f1,0x3b803b6e,0x311531db,0x3be63bdd,0x34d53534,0x3ba03b91,0x2f0e304e,0x3bf43bed,0x34143475,0x3bbc3baf,0x2bd92d7e,0x3bfc3bf8,0x32a13365,0x3bd43bc9,0x224828b6,0x3c003bff,
0x40000,0x60002,0xc0008,0xe000a,0x380034,0x3a0036,0x40003c,0x42003e,0x6c0068,0x6e006a,0x740070,0x760072,0xa0009c,0xa2009e,0xa800a4,0xaa00a6,
0xd400d0,0xd600d2,0xdc00d8,0xde00da,0x1080104,0x10a0106,0x110010c,0x112010e,0x13c0138,0x13e013a,0x1440140,0x1460142,0x170016c,0x172016e,0x1780174,0x17a0176,
0x1a401a0,0x1a601a2,0x1ac01a8,0x1ae01aa,0x1d801d4,0x1da01d6,0x1e001dc,0x1e201de,0x20c0208,0x20e020a,0x2140210,0x2160212,0x240023c,0x242023e,0x2480244,0x24a0246,
0x2740270,0x2760272,0x27c0278,0x27e027a,0x2a802a4,0x2aa02a6,0x2b002ac,0x2b202ae,0x2dc02d8,0x2de02da,0x2e402e0,0x2e602e2,0x310030c,0x312030e,0x3180314,0x31a0316,
0x3440340,0x3460342,0x34c0348,0x34e034a,0x3780374,0x37a0376,0x380037c,0x382037e,0x3ac03a8,0x3ae03aa,0x3b403b0,0x3b603b2,0x3e003dc,0x3e203de,0x3e803e4,0x3ea03e6,
0x4140410,0x4160412,0x41c0418,0x41e041a,0x4480444,0x44a0446,0x450044c,0x452044e,0x47c0478,0x47e047a,0x4840480,0x4860482,0x4b004ac,0x4b204ae,0x4b804b4,0x4ba04b6,
0x4e404e0,0x4e604e2,0x4ec04e8,0x4ee04ea,0x5180514,0x51a0516,0x520051c,0x522051e,0x54c0548,0x54e054a,0x5540550,0x5560552,0x580057c,0x582057e,0x5880584,0x58a0586,
0x5b405b0,0x5b605b2,0x5bc05b8,0x5be05ba,0x5e805e4,0x5ea05e6,0x5f005ec,0x5f205ee,0x61c0618,0x61e061a,0x6240620,0x6260622,0x650064c,0x652064e,0x6580654,0x65a0656,
0x140010,0x160012,0x120010,0x440012,0x480044,0x4a0046,0x460044,0x780046,0x7c0078,0x7e007a,0x7a0078,0xac007a,0xb000ac,0xb200ae,0xae00ac,0xe000ae,
0xe400e0,0xe600e2,0xe200e0,0x11400e2,0x1180114,0x11a0116,0x1160114,0x1480116,0x14c0148,0x14e014a,0x14a0148,0x17c014a,0x180017c,0x182017e,0x17e017c,0x1b0017e,
0x1b401b0,0x1b601b2,0x1b201b0,0x1e401b2,0x1e801e4,0x1ea01e6,0x1e601e4,0x21801e6,0x21c0218,0x21e021a,0x21a0218,0x24c021a,0x250024c,0x252024e,0x24e024c,0x280024e,
0x2840280,0x2860282,0x2820280,0x2b40282,0x2b802b4,0x2ba02b6,0x2b602b4,0x2e802b6,0x2ec02e8,0x2ee02ea,0x2ea02e8,0x31c02ea,0x320031c,0x322031e,0x31e031c,0x350031e,
0x3540350,0x3560352,0x3520350,0x3840352,0x3880384,0x38a0386,0x3860384,0x3b80386,0x3bc03b8,0x3be03ba,0x3ba03b8,0x3ec03ba,0x3f003ec,0x3f203ee,0x3ee03ec,0x42003ee,
0x4240420,0x4260422,0x4220420,0x4540422,0x4580454,0x45a0456,0x4560454,0x4880456,0x48c0488,0x48e048a,0x48a0488,0x4bc048a,0x4c004bc,0x4c204be,0x4be04bc,0x4f004be,
0x4f404f0,0x4f604f2,0x4f204f0,0x52404f2,0x5280524,0x52a0526,0x5260524,0x5580526,0x55c0558,0x55e055a,0x55a0558,0x58c055a,0x590058c,0x592058e,0x58e058c,0x5c0058e,
0x5c405c0,0x5c605c2,0x5c205c0,0x5f405c2,0x5f805f4,0x5fa05f6,0x5f605f4,0x62805f6,0x62c0628,0x62e062a,0x62a0628,0x65c062a,0x660065c,0x662065e,0x65e065c,0x18065e,
0x180018,0x4c001a,0x1a0018,0x4c001a,0x4c004c,0x80004e,0x4e004c,0x80004e,0x800080,0xb40082,0x820080,0xb40082,0xb400b4,0xe800b6,0xb600b4,0xe800b6,
0xe800e8,0x11c00ea,0xea00e8,0x11c00ea,0x11c011c,0x150011e,0x11e011c,0x150011e,0x1500150,0x1840152,0x1520150,0x1840152,0x1840184,0x1b80186,0x1860184,0x1b80186,
0x1b801b8,0x1ec01ba,0x1ba01b8,0x1ec01ba,0x1ec01ec,0x22001ee,0x1ee01ec,0x22001ee,0x2200220,0x2540222,0x2220220,0x2540222,0x2540254,0x2880256,0x2560254,0x2880256,
0x2880288,0x2bc028a,0x28a0288,0x2bc028a,0x2bc02bc,0x2f002be,0x2be02bc,0x2f002be,0x2f002f0,0x32402f2,0x2f202f0,0x32402f2,0x3240324,0x3580326,0x3260324,0x3580326,
0x3580358,0x38c035a,0x35a0358,0x38c035a,0x38c038c,0x3c0038e,0x38e038c,0x3c0038e,0x3c003c0,0x3f403c2,0x3c203c0,0x3f403c2,0x3f403f4,0x42803f6,0x3f603f4,0x42803f6,
0x4280428,0x45c042a,0x42a0428,0x45c042a,0x45c045c,0x490045e,0x45e045c,0x490045e,0x4900490,0x4c40492,0x4920490,0x4c40492,0x4c404c4,0x4f804c6,0x4c604c4,0x4f804c6,
0x4f804f8,0x52c04fa,0x4fa04f8,0x52c04fa,0x52c052c,0x560052e,0x52e052c,0x560052e,0x5600560,0x5940562,0x5620560,0x5940562,0x5940594,0x5c80596,0x5960594,0x5c80596,
0x5c805c8,0x5fc05ca,0x5ca05c8,0x5fc05ca,0x5fc05fc,0x63005fe,0x5fe05fc,0x63005fe,0x6300630,0x6640632,0x6320630,0x6640632,0x6640664,0x1c0666,0x6660664,0x1c0666,
0x1c001c,0x50001e,0x1e001c,0x50001e,0x500050,0x840052,0x520050,0x840052,0x840084,0xb80086,0x860084,0xb80086,0xb800b8,0xec00ba,0xba00b8,0xec00ba,
0xec00ec,0x12000ee,0xee00ec,0x12000ee,0x1200120,0x1540122,0x1220120,0x1540122,0x1540154,0x1880156,0x1560154,0x1880156,0x1880188,0x1bc018a,0x18a0188,0x1bc018a,
0x1bc01bc,0x1f001be,0x1be01bc,0x1f001be,0x1f001f0,0x22401f2,0x1f201f0,0x22401f2,0x2240224,0x2580226,0x2260224,0x2580226,0x2580258,0x28c025a,0x25a0258,0x28c025a,
0x28c028c,0x2c0028e,0x28e028c,0x2c0028e,0x2c002c0,0x2f402c2,0x2c202c0,0x2f402c2,0x2f402f4,0x32802f6,0x2f602f4,0x32802f6,0x3280328,0x35c032a,0x32a0328,0x35c032a,
0x35c035c,0x390035e,0x35e035c,0x390035e,0x3900390,0x3c40392,0x3920390,0x3c40392,0x3c403c4,0x3f803c6,0x3c603c4,0x3f803c6,0x3f803f8,0x42c03fa,0x3fa03f8,0x42c03fa,
0x42c042c,0x460042e,0x42e042c,0x460042e,0x4600460,0x4940462,0x4620460,0x4940462,0x4940494,0x4c80496,0x4960494,0x4c80496,0x4c804c8,0x4fc04ca,0x4ca04c8,0x4fc04ca,
0x4fc04fc,0x53004fe,0x4fe04fc,0x53004fe,0x5300530,0x5640532,0x5320530,0x5640532,0x5640564,0x5980566,0x5660564,0x5980566,0x5980598,0x5cc059a,0x59a0598,0x5cc059a,
0x5cc05cc,0x60005ce,0x5ce05cc,0x60005ce,0x6000600,0x6340602,0x6020600,0x6340602,0x6340634,0x6680636,0x6360634,0x6680636,0x6680668,0x20066a,0x66a0668,0x20066a,
0x5d605d6,0x60a05d6,0x5d605d6,0x60a060a,0x60a060a,0x63e063e,0x60a060a,0x63e063e,0x63e063e,0x672063e,0x63e063e,0x6720672,0x6720672,0x280028,0x6720672,0x280028,
0x5060506,0x53a0506,0x5060506,0x53a053a,0x53a053a,0x56e056e,0x53a053a,0x56e056e,0x56e056e,0x5a2056e,0x56e056e,0x5a205a2,0x5a205a2,0x5d605d6,0x5a205a2,0x5d605d6,
0x4360436,0x46a0436,0x4360436,0x46a046a,0x46a046a,0x49e049e,0x46a046a,0x49e049e,0x49e049e,0x4d2049e,0x49e049e,0x4d204d2,0x4d204d2,0x5060506,0x4d204d2,0x5060506,
0x3660366,0x39a0366,0x3660366,0x39a039a,0x39a039a,0x3ce03ce,0x39a039a,0x3ce03ce,0x3ce03ce,0x40203ce,0x3ce03ce,0x4020402,0x4020402,0x4360436,0x4020402,0x4360436,
0x2960296,0x2ca0296,0x2960296,0x2ca02ca,0x2ca02ca,0x2fe02fe,0x2ca02ca,0x2fe02fe,0x2fe02fe,0x33202fe,0x2fe02fe,0x3320332,0x3320332,0x3660366,0x3320332,0x3660366,
0x1c601c6,0x1fa01c6,0x1c601c6,0x1fa01fa,0x1fa01fa,0x22e022e,0x1fa01fa,0x22e022e,0x22e022e,0x262022e,0x22e022e,0x2620262,0x2620262,0x2960296,0x2620262,0x2960296,
0xf600f6,0x12a00f6,0xf600f6,0x12a012a,0x12a012a,0x15e015e,0x12a012a,0x15e015e,0x15e015e,0x192015e,0x15e015e,0x1920192,0x1920192,0x1c601c6,0x1920192,0x1c601c6,
0x260026,0x5a0026,0x260026,0x5a005a,0x5a005a,0x8e008e,0x5a005a,0x8e008e,0x8e008e,0xc2008e,0x8e008e,0xc200c2,0xc200c2,0xf600f6,0xc200c2,0xf600f6,
0x5d405d4,0x60805d4,0x5d405d4,0x6080608,0x6080608,0x63c063c,0x6080608,0x63c063c,0x63c063c,0x670063c,0x63c063c,0x6700670,0x6700670,0x260026,0x6700670,0x260026,
0x5040504,0x5380504,0x5040504,0x5380538,0x5380538,0x56c056c,0x5380538,0x56c056c,0x56c056c,0x5a0056c,0x56c056c,0x5a005a0,0x5a005a0,0x5d405d4,0x5a005a0,0x5d405d4,
0x4340434,0x4680434,0x4340434,0x4680468,0x4680468,0x49c049c,0x4680468,0x49c049c,0x49c049c,0x4d0049c,0x49c049c,0x4d004d0,0x4d004d0,0x5040504,0x4d004d0,0x5040504,
0x3640364,0x3980364,0x3640364,0x3980398,0x3980398,0x3cc03cc,0x3980398,0x3cc03cc,0x3cc03cc,0x40003cc,0x3cc03cc,0x4000400,0x4000400,0x4340434,0x4000400,0x4340434,
0x2940294,0x2c80294,0x2940294,0x2c802c8,0x2c802c8,0x2fc02fc,0x2c802c8,0x2fc02fc,0x2fc02fc,0x33002fc,0x2fc02fc,0x3300330,0x3300330,0x3640364,0x3300330,0x3640364,
0x1c401c4,0x1f801c4,0x1c401c4,0x1f801f8,0x1f801f8,0x22c022c,0x1f801f8,0x22c022c,0x22c022c,0x260022c,0x22c022c,0x2600260,0x2600260,0x2940294,0x2600260,0x2940294,
0xf400f4,0x12800f4,0xf400f4,0x1280128,0x1280128,0x15c015c,0x1280128,0x15c015c,0x15c015c,0x190015c,0x15c015c,0x1900190,0x1900190,0x1c401c4,0x1900190,0x1c401c4,
0x240024,0x580024,0x240024,0x580058,0x580058,0x8c008c,0x580058,0x8c008c,0x8c008c,0xc0008c,0x8c008c,0xc000c0,0xc000c0,0xf400f4,0xc000c0,0xf400f4,
0x5d205d2,0x60605d2,0x5d205d2,0x6060606,0x6060606,0x63a063a,0x6060606,0x63a063a,0x63a063a,0x66e063a,0x63a063a,0x66e066e,0x66e066e,0x240024,0x66e066e,0x240024,
0x5020502,0x5360502,0x5020502,0x5360536,0x5360536,0x56a056a,0x5360536,0x56a056a,0x56a056a,0x59e056a,0x56a056a,0x59e059e,0x59e059e,0x5d205d2,0x59e059e,0x5d205d2,
0x4320432,0x4660432,0x4320432,0x4660466,0x4660466,0x49a049a,0x4660466,0x49a049a,0x49a049a,0x4ce049a,0x49a049a,0x4ce04ce,0x4ce04ce,0x5020502,0x4ce04ce,0x5020502,
0x3620362,0x3960362,0x3620362,0x3960396,0x3960396,0x3ca03ca,0x3960396,0x3ca03ca,0x3ca03ca,0x3fe03ca,0x3ca03ca,0x3fe03fe,0x3fe03fe,0x4320432,0x3fe03fe,0x4320432,
0x2920292,0x2c60292,0x2920292,0x2c602c6,0x2c602c6,0x2fa02fa,0x2c602c6,0x2fa02fa,0x2fa02fa,0x32e02fa,0x2fa02fa,0x32e032e,0x32e032e,0x3620362,0x32e032e,0x3620362,
0x1c201c2,0x1f601c2,0x1c201c2,0x1f601f6,0x1f601f6,0x22a022a,0x1f601f6,0x22a022a,0x22a022a,0x25e022a,0x22a022a,0x25e025e,0x25e025e,0x2920292,0x25e025e,0x2920292,
0xf200f2,0x12600f2,0xf200f2,0x1260126,0x1260126,0x15a015a,0x1260126,0x15a015a,0x15a015a,0x18e015a,0x15a015a,0x18e018e,0x18e018e,0x1c201c2,0x18e018e,0x1c201c2,
0x220022,0x560022,0x220022,0x560056,0x560056,0x8a008a,0x560056,0x8a008a,0x8a008a,0xbe008a,0x8a008a,0xbe00be,0xbe00be,0xf200f2,0xbe00be,0xf200f2,
0x5d005d0,0x60405d0,0x5d005d0,0x6040604,0x6040604,0x6380638,0x6040604,0x6380638,0x6380638,0x66c0638,0x6380638,0x66c066c,0x66c066c,0x220022,0x66c066c,0x220022,
0x5000500,0x5340500,0x5000500,0x5340534,0x5340534,0x5680568,0x5340534,0x5680568,0x5680568,0x59c0568,0x5680568,0x59c059c,0x59c059c,0x5d005d0,0x59c059c,0x5d005d0,
0x4300430,0x4640430,0x4300430,0x4640464,0x4640464,0x4980498,0x4640464,0x4980498,0x4980498,0x4cc0498,0x4980498,0x4cc04cc,0x4cc04cc,0x5000500,0x4cc04cc,0x5000500,
0x3600360,0x3940360,0x3600360,0x3940394,0x3940394,0x3c803c8,0x3940394,0x3c803c8,0x3c803c8,0x3fc03c8,0x3c803c8,0x3fc03fc,0x3fc03fc,0x4300430,0x3fc03fc,0x4300430,
0x2900290,0x2c40290,0x2900290,0x2c402c4,0x2c402c4,0x2f802f8,0x2c402c4,0x2f802f8,0x2f802f8,0x32c02f8,0x2f802f8,0x32c032c,0x32c032c,0x3600360,0x32c032c,0x3600360,
0x1c001c0,0x1f401c0,0x1c001c0,0x1f401f4,0x1f401f4,0x2280228,0x1f401f4,0x2280228,0x2280228,0x25c0228,0x2280228,0x25c025c,0x25c025c,0x2900290,0x25c025c,0x2900290,
0xf000f0,0x12400f0,0xf000f0,0x1240124,0x1240124,0x1580158,0x1240124,0x1580158,0x1580158,0x18c0158,0x1580158,0x18c018c,0x18c018c,0x1c001c0,0x18c018c,0x1c001c0,
0x200020,0x540020,0x200020,0x540054,0x540054,0x880088,0x540054,0x880088,0x880088,0xbc0088,0x880088,0xbc00bc,0xbc00bc,0xf000f0,0xbc00bc,0xf000f0,
0x30003000,0x30003000,0x30003000,0x30003000,0x30003000,0x30003000,0x30003000,0x30003000,0x0,0x0,0x0,0x0,0x0,0x0,0x0,0x0,
0x30003000,0x30003000,0x30003000,0x30003000,0x30003000,0x30003000,0x30003000,0x30003000,0x0,0x0,0x0,0x0,0x0,0x0,0x0,0x0,
0x2a1f2da8,0xaf64ada8,0xaa1fada8,0x2f642da8,0x2f643000,0xaa1f0000,0xaf64b000,0x2a1f8000,0x2f642da8,0x2a1f2da8,0xaf64ada8,0xaa1fada8,0x2a1f0000,0x2f643000,0xaa1f0000,0xaf64b000,
0x263e2c72,0xafd9aea7,0xa63eac72,0x2fd92ea7,0x2ea72fd9,0xac72a63e,0xaea7afd9,0x2c72263e,0x2fd92ea7,0x263e2c72,0xafd9aea7,0xa63eac72,0x2c72263e,0x2ea72fd9,0xac72a63e,0xaea7afd9,
0x2da80000,0xada80000,0x2da88000,0xada80000,0x2da83000,0xada8b000,0x2da83000,0xada8b000,0x2da83000,0xada8b000,0x2da83000,0xada8b000,0xada80000,0x2da88000,0xada80000,0x2da88000,
0x2f642a1f,0xaf64aa1f,0x2f642a1f,0xaf64aa1f,0x2a1f2f64,0xaa1faf64,0x2a1f2f64,0xaa1faf64,0x2a1f2f64,0xaa1faf64,0x2a1f2f64,0xaa1faf64,0xaf64aa1f,0x2f642a1f,0xaf64aa1f,0x2f642a1f,
0xaa1f2da8,0x2f642da8,0x2a1fada8,0xaf64ada8,0x2f640000,0xaa1fb000,0xaf640000,0x2a1f3000,0xaf64ada8,0xaa1f2da8,0x2f642da8,0x2a1fada8,0x2a1f3000,0x2f648000,0xaa1fb000,0xaf640000,
0xaea7263e,0x2c722fd9,0x2ea7a63e,0xac72afd9,0x2fd92c72,0x263eaea7,0xafd9ac72,0xa63e2ea7,0xac72afd9,0xaea7263e,0x2c722fd9,0x2ea7a63e,0xa63e2ea7,0x2fd92c72,0x263eaea7,0xafd9ac72,
0xada82da8,0xada82da8,0xada82da8,0xada82da8,0x2da8ada8,0x2da8ada8,0x2da8ada8,0x2da8ada8,0x2da82da8,0x2da82da8,0x2da82da8,0x2da82da8,0xada8ada8,0xada8ada8,0xada8ada8,0xada8ada8,
0x3000,0x3000,0x3000,0x80003000,0x8000b000,0x8000b000,0x8000b000,0x8000b000,0x30000000,0x30008000,0x30008000,0x30008000,0xb0000000,0xb0000000,0xb0000000,0xb0000000,
0x2ea7263e,0xac722fd9,0xaea7a63e,0x2c72afd9,0xafd92c72,0xa63eaea7,0x2fd9ac72,0x263e2ea7,0x2c72afd9,0x2ea7263e,0xac722fd9,0xaea7a63e,0x263e2ea7,0xafd92c72,0xa63eaea7,0x2fd9ac72,
0x2f64ada8,0x2a1f2da8,0xaf642da8,0xaa1fada8,0xaa1f3000,0xaf640000,0x2a1fb000,0x2f648000,0xaa1fada8,0x2f64ada8,0x2a1f2da8,0xaf642da8,0x2f640000,0xaa1f3000,0xaf640000,0x2a1fb000,
0xaa1f2f64,0x2a1faf64,0xaa1f2f64,0x2a1faf64,0x2f64aa1f,0xaf642a1f,0x2f64aa1f,0xaf642a1f,0xaf642a1f,0x2f64aa1f,0xaf642a1f,0x2f64aa1f,0xaa1f2f64,0x2a1faf64,0xaa1f2f64,0x2a1faf64,
0x2da80000,0xada80000,0x2da88000,0xada80000,0x2da8b000,0xada83000,0x2da8b000,0xada83000,0xada83000,0x2da8b000,0xada83000,0x2da8b000,0x2da88000,0xada80000,0x2da88000,0xada88000,
0xa63e2c72,0x2fd9aea7,0x263eac72,0xafd92ea7,0xaea72fd9,0x2c72a63e,0x2ea7afd9,0xac72263e,0xafd92ea7,0xa63e2c72,0x2fd9aea7,0x263eac72,0xac72263e,0xaea72fd9,0x2c72a63e,0x2ea7afd9,
0x2f64ada8,0x2a1fada8,0xaf642da8,0xaa1f2da8,0x2a1f0000,0x2f64b000,0xaa1f0000,0xaf643000,0xaa1f2da8,0x2f64ada8,0x2a1fada8,0xaf642da8,0xaf643000,0x2a1f8000,0x2f64b000,0xaa1f8000,
0xb0003000,0xb0003000,0xb0003000,0xb0003000,0xb0003000,0xb0003000,0xb0003000,0xb0003000,0x0,0x8000,0x8000,0x80008000,0x8000,0x8000,0x8000,0x8000,
0x80000000,0x80000000,0x80008000,0x80008000,0x80000000,0x80008000,0x80008000,0x80008000,0xb0003000,0xb0003000,0xb0003000,0xb0003000,0xb0003000,0xb0003000,0xb0003000,0xb0003000,
0xaa1f2da8,0x2f64ada8,0x2a1fada8,0xaf642da8,0xaf643000,0x2a1f0000,0x2f64b000,0xaa1f8000,0xaf642da8,0xaa1f2da8,0x2f64ada8,0x2a1fada8,0xaa1f0000,0xaf643000,0x2a1f0000,0x2f64b000,
0x2fd9aea7,0x263eac72,0xafd92ea7,0xa63e2c72,0x2c72a63e,0x2ea7afd9,0xac72263e,0xaea72fd9,0xa63e2c72,0x2fd9aea7,0x263eac72,0xafd92ea7,0xaea72fd9,0x2c72a63e,0x2ea7afd9,0xac72263e,
0xada80000,0x2da80000,0xada88000,0x2da80000,0xada83000,0x2da8b000,0xada83000,0x2da8b000,0xada83000,0x2da8b000,0xada83000,0x2da8b000,0x2da80000,0xada88000,0x2da88000,0xada88000,
0xaa1f2f64,0x2a1faf64,0xaa1f2f64,0x2a1faf64,0x2f64aa1f,0xaf642a1f,0x2f64aa1f,0xaf642a1f,0x2f64aa1f,0xaf642a1f,0x2f64aa1f,0xaf642a1f,0x2a1faf64,0xaa1f2f64,0x2a1faf64,0xaa1f2f64,
0x2a1f2da8,0xaf642da8,0xaa1fada8,0x2f64ada8,0xaf640000,0x2a1fb000,0x2f640000,0xaa1f3000,0x2f64ada8,0x2a1f2da8,0xaf642da8,0xaa1fada8,0xaa1f3000,0xaf648000,0x2a1fb000,0x2f640000,
0x2c72afd9,0x2ea7263e,0xac722fd9,0xaea7a63e,0x263e2ea7,0xafd92c72,0xa63eaea7,0x2fd9ac72,0xaea7a63e,0x2c72afd9,0x2ea7263e,0xac722fd9,0x2fd9ac72,0x263e2ea7,0xafd92c72,0xa63eaea7,
0x2da8ada8,0x2da8ada8,0x2da8ada8,0x2da8ada8,0xada82da8,0xada82da8,0xada82da8,0xada82da8,0x2da82da8,0x2da82da8,0x2da82da8,0x2da82da8,0xada8ada8,0xada8ada8,0xada8ada8,0xada8ada8,
0x80003000,0x80003000,0x80003000,0x3000,0xb000,0x8000b000,0xb000,0xb000,0xb0000000,0xb0008000,0xb0008000,0xb0008000,0x30000000,0x30000000,0x30000000,0x30008000,
0x2c722fd9,0x2ea7a63e,0xac72afd9,0xaea7263e,0x263eaea7,0xafd9ac72,0xa63e2ea7,0x2fd92c72,0xaea7263e,0x2c722fd9,0x2ea7a63e,0xac72afd9,0x2fd92c72,0x263eaea7,0xafd9ac72,0xa63e2ea7,
0xaf64ada8,0xaa1f2da8,0x2f642da8,0x2a1fada8,0x2a1f3000,0x2f648000,0xaa1fb000,0xaf648000,0x2a1fada8,0xaf64ada8,0xaa1f2da8,0x2f642da8,0xaf640000,0x2a1f3000,0x2f648000,0xaa1fb000,
0x2f642a1f,0xaf64aa1f,0x2f642a1f,0xaf64aa1f,0x2a1f2f64,0xaa1faf64,0x2a1f2f64,0xaa1faf64,0xaa1faf64,0x2a1f2f64,0xaa1faf64,0x2a1f2f64,0x2f642a1f,0xaf64aa1f,0x2f642a1f,0xaf64aa1f,
0xada80000,0x2da80000,0xada88000,0x2da88000,0xada8b000,0x2da83000,0xada8b000,0x2da83000,0x2da83000,0xada8b000,0x2da83000,0xada8b000,0xada88000,0x2da88000,0xada88000,0x2da80000,
0x2fd92ea7,0x263e2c72,0xafd9aea7,0xa63eac72,0x2c72263e,0x2ea72fd9,0xac72a63e,0xaea7afd9,0xa63eac72,0x2fd92ea7,0x263e2c72,0xafd9aea7,0xaea7afd9,0x2c72263e,0x2ea72fd9,0xac72a63e,
0xaf64ada8,0xaa1fada8,0x2f642da8,0x2a1f2da8,0xaa1f0000,0xaf64b000,0x2a1f0000,0x2f643000,0x2a1f2da8,0xaf64ada8,0xaa1fada8,0x2f642da8,0x2f643000,0xaa1f8000,0xaf64b000,0x2a1f0000,
0x80008000,0x80008000,0x80008000,0x80008000,0x80008000,0x80008000,0x80008000,0x80008000,0x30003000,0x30003000,0x30003000,0x30003000,0x30003000,0x30003000,0x30003000,0x30003000,
0x80008000,0x80008000,0x80008000,0x80008000,0x80008000,0x80008000,0x80008000,0x80008000,0x30003000,0x30003000,0x30003000,0x30003000,0x30003000,0x30003000,0x30003000,0x30003000,
0xaf64ada8,0xaa1fada8,0x2f642da8,0x2a1f2da8,0xaa1f8000,0xaf64b000,0x2a1f8000,0x2f643000,0x2a1f2da8,0xaf64ada8,0xaa1fada8,0x2f642da8,0x2f643000,0xaa1f0000,0xaf64b000,0x2a1f8000,
0xafd9aea7,0xa63eac72,0x2fd92ea7,0x263e2c72,0xac72a63e,0xaea7afd9,0x2c72263e,0x2ea72fd9,0x263e2c72,0xafd9aea7,0xa63eac72,0x2fd92ea7,0x2ea72fd9,0xac72a63e,0xaea7afd9,0x2c72263e,
0x2da83000,0xada8b000,0x2da83000,0xada8b000,0xada80000,0x2da88000,0xada80000,0x2da88000,0xada88000,0x2da88000,0xada80000,0x2da88000,0xada8b000,0x2da83000,0xada8b000,0x2da83000,
0x2a1f2f64,0xaa1faf64,0x2a1f2f64,0xaa1faf64,0xaf64aa1f,0x2f642a1f,0xaf64aa1f,0x2f642a1f,0xaf64aa1f,0x2f642a1f,0xaf64aa1f,0x2f642a1f,0xaa1faf64,0x2a1f2f64,0xaa1faf64,0x2a1f2f64,
0xaf64ada8,0xaa1f2da8,0x2f642da8,0x2a1fada8,0x2a1f3000,0x2f648000,0xaa1fb000,0xaf640000,0x2a1fada8,0xaf64ada8,0xaa1f2da8,0x2f642da8,0xaf648000,0x2a1f3000,0x2f648000,0xaa1fb000,
0xac72afd9,0xaea7263e,0x2c722fd9,0x2ea7a63e,0xa63e2ea7,0x2fd92c72,0x263eaea7,0xafd9ac72,0x2ea7a63e,0xac72afd9,0xaea7263e,0x2c722fd9,0xafd9ac72,0xa63e2ea7,0x2fd92c72,0x263eaea7,
0xada8ada8,0xada8ada8,0xada8ada8,0xada8ada8,0x2da82da8,0x2da82da8,0x2da82da8,0x2da82da8,0xada82da8,0xada82da8,0xada82da8,0xada82da8,0x2da8ada8,0x2da8ada8,0x2da8ada8,0x2da8ada8,
0xb0008000,0xb0000000,0xb0000000,0xb0000000,0x30008000,0x30008000,0x30008000,0x30008000,0x3000,0x3000,0x3000,0x80003000,0x8000b000,0x8000b000,0x8000b000,0x8000b000,
0xac722fd9,0xaea7a63e,0x2c72afd9,0x2ea7263e,0xa63eaea7,0x2fd9ac72,0x263e2ea7,0xafd92c72,0x2ea7263e,0xac722fd9,0xaea7a63e,0x2c72afd9,0xafd92c72,0xa63eaea7,0x2fd9ac72,0x263e2ea7,
0x2a1f2da8,0xaf642da8,0xaa1fada8,0x2f64ada8,0xaf648000,0x2a1fb000,0x2f648000,0xaa1f3000,0x2f64ada8,0x2a1f2da8,0xaf642da8,0xaa1fada8,0xaa1f3000,0xaf640000,0x2a1fb000,0x2f648000,
0xaf642a1f,0x2f64aa1f,0xaf642a1f,0x2f64aa1f,0xaa1f2f64,0x2a1faf64,0xaa1f2f64,0x2a1faf64,0x2a1faf64,0xaa1f2f64,0x2a1faf64,0xaa1f2f64,0xaf642a1f,0x2f64aa1f,0xaf642a1f,0x2f64aa1f,
0xada83000,0x2da8b000,0xada83000,0x2da8b000,0x2da88000,0xada80000,0x2da88000,0xada88000,0xada88000,0x2da88000,0xada80000,0x2da88000,0xada83000,0x2da8b000,0xada83000,0x2da8b000,
0xafd92ea7,0xa63e2c72,0x2fd9aea7,0x263eac72,0xac72263e,0xaea72fd9,0x2c72a63e,0x2ea7afd9,0x263eac72,0xafd92ea7,0xa63e2c72,0x2fd9aea7,0x2ea7afd9,0xac72263e,0xaea72fd9,0x2c72a63e,
0xaa1f2da8,0x2f64ada8,0x2a1fada8,0xaf642da8,0xaf643000,0x2a1f8000,0x2f64b000,0xaa1f8000,0xaf642da8,0xaa1f2da8,0x2f64ada8,0x2a1fada8,0xaa1f8000,0xaf643000,0x2a1f8000,0x2f64b000,
0x80008000,0x80000000,0x80000000,0x0,0x80000000,0x80000000,0x80000000,0x80000000,0xb0003000,0xb0003000,0xb0003000,0xb0003000,0xb0003000,0xb0003000,0xb0003000,0xb0003000,
0x3000b000,0x3000b000,0x3000b000,0x3000b000,0x3000b000,0x3000b000,0x3000b000,0x3000b000,0x80000000,0x80000000,0x80008000,0x80008000,0x80000000,0x80008000,0x80008000,0x80008000,
0x2f64ada8,0x2a1fada8,0xaf642da8,0xaa1f2da8,0x2a1f8000,0x2f64b000,0xaa1f8000,0xaf643000,0xaa1f2da8,0x2f64ada8,0x2a1fada8,0xaf642da8,0xaf643000,0x2a1f0000,0x2f64b000,0xaa1f8000,
0x263eac72,0xafd92ea7,0xa63e2c72,0x2fd9aea7,0x2ea7afd9,0xac72263e,0xaea72fd9,0x2c72a63e,0x2fd9aea7,0x263eac72,0xafd92ea7,0xa63e2c72,0x2c72a63e,0x2ea7afd9,0xac72263e,0xaea72fd9,
0xada83000,0x2da8b000,0xada83000,0x2da8b000,0x2da80000,0xada88000,0x2da88000,0xada88000,0x2da88000,0xada88000,0x2da80000,0xada88000,0x2da8b000,0xada83000,0x2da8b000,0xada83000,
0x2f64aa1f,0xaf642a1f,0x2f64aa1f,0xaf642a1f,0x2a1faf64,0xaa1f2f64,0x2a1faf64,0xaa1f2f64,0x2a1faf64,0xaa1f2f64,0x2a1faf64,0xaa1f2f64,0xaf642a1f,0x2f64aa1f,0xaf642a1f,0x2f64aa1f,
0x2f64ada8,0x2a1f2da8,0xaf642da8,0xaa1fada8,0xaa1f3000,0xaf648000,0x2a1fb000,0x2f640000,0xaa1fada8,0x2f64ada8,0x2a1f2da8,0xaf642da8,0x2f648000,0xaa1f3000,0xaf648000,0x2a1fb000,
0xaea7a63e,0x2c72afd9,0x2ea7263e,0xac722fd9,0x2fd9ac72,0x263e2ea7,0xafd92c72,0xa63eaea7,0xac722fd9,0xaea7a63e,0x2c72afd9,0x2ea7263e,0xa63eaea7,0x2fd9ac72,0x263e2ea7,0xafd92c72,
0xada8ada8,0xada8ada8,0xada8ada8,0xada8ada8,0x2da82da8,0x2da82da8,0x2da82da8,0x2da82da8,0x2da8ada8,0x2da8ada8,0x2da8ada8,0x2da8ada8,0xada82da8,0xada82da8,0xada82da8,0xada82da8,
0x30008000,0x30000000,0x30000000,0x30000000,0xb0008000,0xb0008000,0xb0008000,0xb0000000,0x80003000,0x80003000,0x80003000,0x3000,0xb000,0x8000b000,0xb000,0xb000,
0x2ea7a63e,0xac72afd9,0xaea7263e,0x2c722fd9,0xafd9ac72,0xa63e2ea7,0x2fd92c72,0x263eaea7,0x2c722fd9,0x2ea7a63e,0xac72afd9,0xaea7263e,0x263eaea7,0xafd9ac72,0xa63e2ea7,0x2fd92c72,
0xaa1f2da8,0x2f642da8,0x2a1fada8,0xaf64ada8,0x2f648000,0xaa1fb000,0xaf640000,0x2a1f3000,0xaf64ada8,0xaa1f2da8,0x2f642da8,0x2a1fada8,0x2a1f3000,0x2f648000,0xaa1fb000,0xaf648000,
0xaa1faf64,0x2a1f2f64,0xaa1faf64,0x2a1f2f64,0x2f642a1f,0xaf64aa1f,0x2f642a1f,0xaf64aa1f,0xaf64aa1f,0x2f642a1f,0xaf64aa1f,0x2f642a1f,0xaa1faf64,0x2a1f2f64,0xaa1faf64,0x2a1f2f64,
0x2da83000,0xada8b000,0x2da83000,0xada8b000,0xada88000,0x2da88000,0xada88000,0x2da80000,0x2da88000,0xada88000,0x2da80000,0xada80000,0x2da83000,0xada8b000,0x2da83000,0xada8b000,
0xa63eac72,0x2fd92ea7,0x263e2c72,0xafd9aea7,0xaea7afd9,0x2c72263e,0x2ea72fd9,0xac72a63e,0xafd9aea7,0xa63eac72,0x2fd92ea7,0x263e2c72,0xac72a63e,0xaea7afd9,0x2c72263e,0x2ea72fd9,
0x2a1f2da8,0xaf64ada8,0xaa1fada8,0x2f642da8,0x2f643000,0xaa1f8000,0xaf64b000,0x2a1f0000,0x2f642da8,0x2a1f2da8,0xaf64ada8,0xaa1fada8,0x2a1f8000,0x2f643000,0xaa1f8000,0xaf64b000,
0x3c003c00,0x3c003c00,0x3c003c00,0x3c003c00,0x3c003c00,0x3c003c00,0x3c003c00,0x3c003c00,0x80008000,0x80008000,0x80008000,0x80008000,0x80008000,0x80008000,0x80008000,0x80008000,
0x3bd93c00,0x3aa73b64,0x387239a8,0x323e361f,0xb23e0000,0xb872b61f,0xbaa7b9a8,0xbbd9bb64,0xb23e8000,0xb872b61f,0xbaa7b9a8,0xbbd9bb64,0xbbd9bc00,0xbaa7bb64,0xb872b9a8,0xb23eb61f,
0xbb64bc00,0xb61fb9a8,0x361f8000,0x3b6439a8,0x3b643c00,0x361f39a8,0xb61f0000,0xbb64b9a8,0x361f8000,0x3b6439a8,0x3b643c00,0x361f39a8,0xb61f8000,0xbb64b9a8,0xbb64bc00,0xb61fb9a8,
0x38728000,0x3bd93b64,0x323e39a8,0xbaa7b61f,0x3aa73c00,0xb23e361f,0xbbd9b9a8,0xb872bb64,0x3aa73c00,0xb23e361f,0xbbd9b9a8,0xb872bb64,0xb8728000,0xbbd9bb64,0xb23eb9a8,0x3aa7361f,
0xbc008000,0x3c008000,0xbc000000,0x3c008000,0xbc000000,0x3c008000,0xbc000000,0x3c008000,0x3c00,0x8000bc00,0x3c00,0x8000bc00,0x3c00,0x8000bc00,0x80003c00,0x8000bc00,
0xbbd98000,0x3aa7361f,0xb872b9a8,0x323e3b64,0x323ebc00,0xb8723b64,0x3aa7b9a8,0xbbd9361f,0xb23e3c00,0x3872bb64,0xbaa739a8,0x3bd9b61f,0xbbd90000,0x3aa7361f,0xb872b9a8,0x323e3b64,
0x3b648000,0xb61fb9a8,0xb61f3c00,0x3b64b9a8,0xbb648000,0x361f39a8,0x361fbc00,0xbb6439a8,0x361fbc00,0xbb6439a8,0x3b648000,0xb61fb9a8,0xb61f3c00,0x3b64b9a8,0xbb640000,0x361f39a8,
0xb8723c00,0x3bd9b61f,0xb23eb9a8,0xbaa73b64,0xbaa78000,0xb23e3b64,0x3bd9b9a8,0xb872b61f,0x3aa78000,0x323ebb64,0xbbd939a8,0x3872361f,0xb8723c00,0x3bd9b61f,0xb23eb9a8,0xbaa73b64,
0xbbd93c00,0xbaa73b64,0xb87239a8,0xb23e361f,0x323e8000,0x3872b61f,0x3aa7b9a8,0x3bd9bb64,0x323e8000,0x3872b61f,0x3aa7b9a8,0x3bd9bb64,0x3bd9bc00,0x3aa7bb64,0x3872b9a8,0x323eb61f,
0xbc003c00,0xbc003c00,0xbc003c00,0xbc003c00,0xbc003c00,0xbc003c00,0xbc003c00,0xbc003c00,0x80008000,0x80000000,0x80000000,0x80000000,0x80000000,0x80000000,0x0,0x80000000,
0xb8728000,0xbbd93b64,0xb23e39a8,0x3aa7b61f,0xbaa73c00,0x323e361f,0x3bd9b9a8,0x3872bb64,0xbaa73c00,0x323e361f,0x3bd9b9a8,0x3872bb64,0x38728000,0x3bd9bb64,0x323eb9a8,0xbaa7361f,
0x3b64bc00,0x361fb9a8,0xb61f8000,0xbb6439a8,0xbb643c00,0xb61f39a8,0x361f0000,0x3b64b9a8,0xb61f8000,0xbb6439a8,0xbb643c00,0xb61f39a8,0x361f8000,0x3b64b9a8,0x3b64bc00,0x361fb9a8,
0x3bd98000,0xbaa7361f,0x3872b9a8,0xb23e3b64,0xb23ebc00,0x38723b64,0xbaa7b9a8,0x3bd9361f,0x323e3c00,0xb872bb64,0x3aa739a8,0xbbd9b61f,0x3bd98000,0xbaa7361f,0x3872b9a8,0xb23e3b64,
0x3c008000,0xbc008000,0x3c000000,0xbc008000,0x3c000000,0xbc008000,0x3c000000,0xbc000000,0x80003c00,0xbc00,0x80003c00,0x8000bc00,0x80003c00,0xbc00,0x80003c00,0xbc00,
0x38723c00,0xbbd9b61f,0x323eb9a8,0x3aa73b64,0x3aa78000,0x323e3b64,0xbbd9b9a8,0x3872b61f,0xbaa78000,0xb23ebb64,0x3bd939a8,0xb872361f,0x38723c00,0xbbd9b61f,0x323eb9a8,0x3aa73b64,
0xbb640000,0x361fb9a8,0x361f3c00,0xbb64b9a8,0x3b648000,0xb61f39a8,0xb61fbc00,0x3b6439a8,0xb61fbc00,0x3b6439a8,0xbb640000,0x361fb9a8,0x361f3c00,0xbb64b9a8,0x3b648000,0xb61f39a8,
0x39a83c00,0xb9a80000,0xb9a8bc00,0x39a88000,0x39a83c00,0xb9a80000,0xb9a8bc00,0x39a88000,0xb9a88000,0xb9a8bc00,0x39a88000,0x39a83c00,0xb9a80000,0xb9a8bc00,0x39a88000,0x39a83c00,
0x38723c00,0xbbd9b61f,0x323eb9a8,0x3aa73b64,0xbaa70000,0xb23ebb64,0x3bd939a8,0xb872361f,0xbaa78000,0xb23ebb64,0x3bd939a8,0xb872361f,0xb872bc00,0x3bd9361f,0xb23e39a8,0xbaa7bb64,
0xb61fbc00,0x3b6439a8,0xbb640000,0x361fb9a8,0x361f3c00,0xbb64b9a8,0x3b648000,0xb61f39a8,0x3b648000,0xb61f39a8,0xb61fbc00,0x3b6439a8,0xbb648000,0x361fb9a8,0x361f3c00,0xbb64b9a8,
0x3bd98000,0xbaa7361f,0x3872b9a8,0xb23e3b64,0x323e3c00,0xb872bb64,0x3aa739a8,0xbbd9b61f,0x323e3c00,0xb872bb64,0x3aa739a8,0xbbd9b61f,0xbbd98000,0x3aa7b61f,0xb87239a8,0x323ebb64,
0xb9a88000,0xb9a83c00,0x39a88000,0x39a8bc00,0xb9a80000,0xb9a83c00,0x39a88000,0x39a8bc00,0xb9a83c00,0x39a88000,0x39a8bc00,0xb9a80000,0xb9a83c00,0x39a88000,0x39a8bc00,0xb9a88000,
0xb8728000,0xbbd93b64,0xb23e39a8,0x3aa7b61f,0x3aa7bc00,0xb23eb61f,0xbbd939a8,0xb8723b64,0xbaa73c00,0x323e361f,0x3bd9b9a8,0x3872bb64,0xb8728000,0xbbd93b64,0xb23e39a8,0x3aa7b61f,
0x361f8000,0x3b64b9a8,0x3b64bc00,0x361fb9a8,0xb61f8000,0xbb6439a8,0xbb643c00,0xb61f39a8,0x3b64bc00,0x361fb9a8,0xb61f8000,0xbb6439a8,0xbb643c00,0xb61f39a8,0x361f8000,0x3b64b9a8,
0xbbd93c00,0xbaa73b64,0xb87239a8,0xb23e361f,0xb23e8000,0xb872361f,0xbaa739a8,0xbbd93b64,0x323e8000,0x3872b61f,0x3aa7b9a8,0x3bd9bb64,0xbbd93c00,0xbaa73b64,0xb87239a8,0xb23e361f,
0xb8723c00,0x3bd9b61f,0xb23eb9a8,0xbaa73b64,0x3aa78000,0x323ebb64,0xbbd939a8,0x3872361f,0x3aa78000,0x323ebb64,0xbbd939a8,0x3872361f,0x3872bc00,0xbbd9361f,0x323e39a8,0x3aa7bb64,
0xb9a83c00,0x39a80000,0x39a8bc00,0xb9a88000,0xb9a83c00,0x39a88000,0x39a8bc00,0xb9a88000,0x39a88000,0x39a8bc00,0xb9a88000,0xb9a83c00,0x39a80000,0x39a8bc00,0xb9a88000,0xb9a83c00,
0xbbd98000,0x3aa7361f,0xb872b9a8,0x323e3b64,0xb23e3c00,0x3872bb64,0xbaa739a8,0x3bd9b61f,0xb23e3c00,0x3872bb64,0xbaa739a8,0x3bd9b61f,0x3bd98000,0xbaa7b61f,0x387239a8,0xb23ebb64,
0x361fbc00,0xbb6439a8,0x3b640000,0xb61fb9a8,0xb61f3c00,0x3b64b9a8,0xbb648000,0x361f39a8,0xbb648000,0x361f39a8,0x361fbc00,0xbb6439a8,0x3b648000,0xb61fb9a8,0xb61f3c00,0x3b64b9a8,
0x38728000,0x3bd93b64,0x323e39a8,0xbaa7b61f,0xbaa7bc00,0x323eb61f,0x3bd939a8,0x38723b64,0x3aa73c00,0xb23e361f,0xbbd9b9a8,0xb872bb64,0x38728000,0x3bd93b64,0x323e39a8,0xbaa7b61f,
0x39a88000,0x39a83c00,0xb9a88000,0xb9a8bc00,0x39a80000,0x39a83c00,0xb9a80000,0xb9a8bc00,0x39a83c00,0xb9a88000,0xb9a8bc00,0x39a88000,0x39a83c00,0xb9a88000,0xb9a8bc00,0x39a80000,
0x3bd93c00,0x3aa73b64,0x387239a8,0x323e361f,0x323e8000,0x3872361f,0x3aa739a8,0x3bd93b64,0xb23e8000,0xb872b61f,0xbaa7b9a8,0xbbd9bb64,0x3bd93c00,0x3aa73b64,0x387239a8,0x323e361f,
0xb61f8000,0xbb64b9a8,0xbb64bc00,0xb61fb9a8,0x361f8000,0x3b6439a8,0x3b643c00,0x361f39a8,0xbb64bc00,0xb61fb9a8,0x361f0000,0x3b6439a8,0x3b643c00,0x361f39a8,0xb61f8000,0xbb64b9a8,
0x0,0x0,0x0,0x0,0x0,0x0,0x0,0x0,0x3c003c00,0x3c003c00,0x3c003c00,0x3c003c00,0x3c003c00,0x3c003c00,0x3c003c00,0x3c003c00,
0x323e0000,0x3872361f,0x3aa739a8,0x3bd93b64,0x3bd93c00,0x3aa73b64,0x387239a8,0x323e361f,0x3bd93c00,0x3aa73b64,0x387239a8,0x323e361f,0xb23e0000,0xb872b61f,0xbaa7b9a8,0xbbd9bb64,
0xb61f0000,0xbb64b9a8,0xbb64bc00,0xb61fb9a8,0x361f0000,0x3b6439a8,0x3b643c00,0x361f39a8,0xbb64bc00,0xb61fb9a8,0x361f8000,0x3b6439a8,0x3b643c00,0x361f39a8,0xb61f0000,0xbb64b9a8,
0xbaa7bc00,0x323eb61f,0x3bd939a8,0x38723b64,0x38720000,0x3bd93b64,0x323e39a8,0xbaa7b61f,0x38728000,0x3bd93b64,0x323e39a8,0xbaa7b61f,0x3aa73c00,0xb23e361f,0xbbd9b9a8,0xb872bb64,
0x3c00,0x8000bc00,0x3c00,0x8000bc00,0x3c00,0x8000bc00,0x80003c00,0x8000bc00,0x3c000000,0xbc000000,0x3c008000,0xbc000000,0x3c008000,0xbc000000,0x3c008000,0xbc000000,
0xb23e3c00,0x3872bb64,0xbaa739a8,0x3bd9b61f,0xbbd90000,0x3aa7361f,0xb872b9a8,0x323e3b64,0x3bd90000,0xbaa7b61f,0x387239a8,0xb23ebb64,0xb23e3c00,0x3872bb64,0xbaa739a8,0x3bd9b61f,
0x361fbc00,0xbb6439a8,0x3b648000,0xb61fb9a8,0xb61f3c00,0x3b64b9a8,0xbb640000,0x361f39a8,0xbb640000,0x361f39a8,0x361fbc00,0xbb6439a8,0x3b640000,0xb61fb9a8,0xb61f3c00,0x3b64b9a8,
0x3aa78000,0x323ebb64,0xbbd939a8,0x3872361f,0xb8723c00,0x3bd9b61f,0xb23eb9a8,0xbaa73b64,0x3872bc00,0xbbd9361f,0x323e39a8,0x3aa7bb64,0x3aa70000,0x323ebb64,0xbbd939a8,0x3872361f,
0xb23e0000,0xb872361f,0xbaa739a8,0xbbd93b64,0xbbd93c00,0xbaa73b64,0xb87239a8,0xb23e361f,0xbbd93c00,0xbaa73b64,0xb87239a8,0xb23e361f,0x323e8000,0x3872b61f,0x3aa7b9a8,0x3bd9bb64,
0x0,0x8000,0x8000,0x8000,0x8000,0x8000,0x80008000,0x8000,0xbc003c00,0xbc003c00,0xbc003c00,0xbc003c00,0xbc003c00,0xbc003c00,0xbc003c00,0xbc003c00,
0x3aa7bc00,0xb23eb61f,0xbbd939a8,0xb8723b64,0xb8720000,0xbbd93b64,0xb23e39a8,0x3aa7b61f,0xb8728000,0xbbd93b64,0xb23e39a8,0x3aa7b61f,0xbaa73c00,0x323e361f,0x3bd9b9a8,0x3872bb64,
0x361f0000,0x3b64b9a8,0x3b64bc00,0x361fb9a8,0xb61f0000,0xbb6439a8,0xbb643c00,0xb61f39a8,0x3b64bc00,0x361fb9a8,0xb61f8000,0xbb6439a8,0xbb643c00,0xb61f39a8,0x361f0000,0x3b64b9a8,
0x323e3c00,0xb872bb64,0x3aa739a8,0xbbd9b61f,0x3bd98000,0xbaa7361f,0x3872b9a8,0xb23e3b64,0xbbd90000,0x3aa7b61f,0xb87239a8,0x323ebb64,0x323e3c00,0xb872bb64,0x3aa739a8,0xbbd9b61f,
0x80003c00,0xbc00,0x80003c00,0x8000bc00,0x80003c00,0xbc00,0x80003c00,0xbc00,0xbc000000,0x3c000000,0xbc008000,0x3c000000,0xbc008000,0x3c000000,0xbc008000,0x3c008000,
0xbaa78000,0xb23ebb64,0x3bd939a8,0xb872361f,0x38723c00,0xbbd9b61f,0x323eb9a8,0x3aa73b64,0xb872bc00,0x3bd9361f,0xb23e39a8,0xbaa7bb64,0xbaa70000,0xb23ebb64,0x3bd939a8,0xb872361f,
0xb61fbc00,0x3b6439a8,0xbb640000,0x361fb9a8,0x361f3c00,0xbb64b9a8,0x3b648000,0xb61f39a8,0x3b648000,0xb61f39a8,0xb61fbc00,0x3b6439a8,0xbb640000,0x361fb9a8,0x361f3c00,0xbb64b9a8,
0x39a80000,0x39a83c00,0xb9a80000,0xb9a8bc00,0x39a88000,0x39a83c00,0xb9a80000,0xb9a8bc00,0x39a83c00,0xb9a80000,0xb9a8bc00,0x39a88000,0x39a83c00,0xb9a80000,0xb9a8bc00,0x39a88000,
0x3aa70000,0x323e3b64,0xbbd9b9a8,0x3872b61f,0x38723c00,0xbbd9b61f,0x323eb9a8,0x3aa73b64,0x38723c00,0xbbd9b61f,0x323eb9a8,0x3aa73b64,0xbaa70000,0xb23ebb64,0x3bd939a8,0xb872361f,
0xbb640000,0x361fb9a8,0x361f3c00,0xbb64b9a8,0x3b640000,0xb61f39a8,0xb61fbc00,0x3b6439a8,0xb61fbc00,0x3b6439a8,0xbb640000,0x361fb9a8,0x361f3c00,0xbb64b9a8,0x3b648000,0xb61f39a8,
0xb23ebc00,0x38723b64,0xbaa7b9a8,0x3bd9361f,0x3bd90000,0xbaa7361f,0x3872b9a8,0xb23e3b64,0x3bd98000,0xbaa7361f,0x3872b9a8,0xb23e3b64,0x323e3c00,0xb872bb64,0x3aa739a8,0xbbd9b61f,
0xb9a83c00,0x39a88000,0x39a8bc00,0xb9a80000,0xb9a83c00,0x39a88000,0x39a8bc00,0xb9a88000,0x39a80000,0x39a8bc00,0xb9a80000,0xb9a83c00,0x39a88000,0x39a8bc00,0xb9a80000,0xb9a83c00,
0xbaa73c00,0x323e361f,0x3bd9b9a8,0x3872bb64,0xb8728000,0xbbd93b64,0xb23e39a8,0x3aa7b61f,0x38720000,0x3bd9bb64,0x323eb9a8,0xbaa7361f,0xbaa73c00,0x323e361f,0x3bd9b9a8,0x3872bb64,
0x3b64bc00,0x361fb9a8,0xb61f8000,0xbb6439a8,0xbb643c00,0xb61f39a8,0x361f8000,0x3b64b9a8,0xb61f0000,0xbb6439a8,0xbb643c00,0xb61f39a8,0x361f0000,0x3b64b9a8,0x3b64bc00,0x361fb9a8,
0x323e8000,0x3872b61f,0x3aa7b9a8,0x3bd9bb64,0xbbd93c00,0xbaa73b64,0xb87239a8,0xb23e361f,0x3bd9bc00,0x3aa7bb64,0x3872b9a8,0x323eb61f,0x323e0000,0x3872b61f,0x3aa7b9a8,0x3bd9bb64,
0xbaa70000,0xb23e3b64,0x3bd9b9a8,0xb872b61f,0xb8723c00,0x3bd9b61f,0xb23eb9a8,0xbaa73b64,0xb8723c00,0x3bd9b61f,0xb23eb9a8,0xbaa73b64,0x3aa78000,0x323ebb64,0xbbd939a8,0x3872361f,
0xb9a80000,0xb9a83c00,0x39a80000,0x39a8bc00,0xb9a88000,0xb9a83c00,0x39a80000,0x39a8bc00,0xb9a83c00,0x39a80000,0x39a8bc00,0xb9a88000,0xb9a83c00,0x39a88000,0x39a8bc00,0xb9a88000,
0x323ebc00,0xb8723b64,0x3aa7b9a8,0xbbd9361f,0xbbd90000,0x3aa7361f,0xb872b9a8,0x323e3b64,0xbbd98000,0x3aa7361f,0xb872b9a8,0x323e3b64,0xb23e3c00,0x3872bb64,0xbaa739a8,0x3bd9b61f,
0x3b640000,0xb61fb9a8,0xb61f3c00,0x3b64b9a8,0xbb640000,0x361f39a8,0x361fbc00,0xbb6439a8,0x361fbc00,0xbb6439a8,0x3b640000,0xb61fb9a8,0xb61f3c00,0x3b64b9a8,0xbb648000,0x361f39a8,
0x3aa73c00,0xb23e361f,0xbbd9b9a8,0xb872bb64,0x38728000,0x3bd93b64,0x323e39a8,0xbaa7b61f,0xb8720000,0xbbd9bb64,0xb23eb9a8,0x3aa7361f,0x3aa73c00,0xb23e361f,0xbbd9b9a8,0xb872bb64,
0x39a83c00,0xb9a88000,0xb9a8bc00,0x39a88000,0x39a83c00,0xb9a88000,0xb9a8bc00,0x39a80000,0xb9a80000,0xb9a8bc00,0x39a80000,0x39a83c00,0xb9a88000,0xb9a8bc00,0x39a88000,0x39a83c00,
0xb23e8000,0xb872b61f,0xbaa7b9a8,0xbbd9bb64,0x3bd93c00,0x3aa73b64,0x387239a8,0x323e361f,0xbbd9bc00,0xbaa7bb64,0xb872b9a8,0xb23eb61f,0xb23e0000,0xb872b61f,0xbaa7b9a8,0xbbd9bb64,
0xbb64bc00,0xb61fb9a8,0x361f0000,0x3b6439a8,0x3b643c00,0x361f39a8,0xb61f8000,0xbb64b9a8,0x361f0000,0x3b6439a8,0x3b643c00,0x361f39a8,0xb61f0000,0xbb64b9a8,0xbb64bc00,0xb61fb9a8,
};
__device__ __align__(1024) bf16 g_x1T[DM * XP];
__device__ __align__(1024) bf16 g_x2T[DM * XP];
__device__ __align__(1024) unsigned g_xcnt[10][4][32];
__device__ __align__(1024) uint4 g_of[8][16][1280];
__device__ __align__(1024) float g_fs[2][SEQ];

#define COUNT(i)
#define TS_SMEM 0
#define TS_DECL
#define TS_ARG
#define TS_PASS
#define TS_PHASE(p)
#define TS(i)
#define TSX(row, i)
#define TS_BEGIN
#define TS_END

struct cplx { float r, i; };
__device__ __forceinline__ cplx cmul(cplx a, cplx b) {
    cplx o;
    o.r = fmaf(a.r, b.r, -a.i * b.i);
    o.i = fmaf(a.r, b.i, a.i * b.r);
    return o;
}
__device__ __forceinline__ cplx csq(cplx a) {
    cplx o;
    o.r = fmaf(a.r, a.r, -a.i * a.i);
    o.i = 2.f * a.r * a.i;
    return o;
}
__device__ __forceinline__ cplx cexp_p(float arl, float ai, float p) {
    float mag = ex2(arl * p);
    float ang = ai * p;
    float n = rintf(ang * 0.15915494309189535f);
    float r = fmaf(n, -6.2831854820251465f, ang);
    r = fmaf(n, 1.7484555e-7f, r);
    cplx o;
    o.r = mag * __cosf(r);
    o.i = mag * __sinf(r);
    return o;
}

__device__ __forceinline__ uint32_t pack2h(float lo, float hi) {
    uint32_t r;
    asm("cvt.rn.f16x2.f32 %0, %1, %2;" : "=r"(r) : "f"(hi), "f"(lo));
    return r;
}
__device__ __forceinline__ uint32_t hmul(uint32_t a, uint32_t b) { uint32_t d; asm("mul.rn.f16x2 %0, %1, %2;" : "=r"(d) : "r"(a), "r"(b)); return d; }
__device__ __forceinline__ uint32_t hfma(uint32_t a, uint32_t b, uint32_t c) { uint32_t d; asm("fma.rn.f16x2 %0, %1, %2, %3;" : "=r"(d) : "r"(a), "r"(b), "r"(c)); return d; }
__device__ __forceinline__ uint32_t hfms(uint32_t a, uint32_t b, uint32_t c) {
    uint32_t d;
    asm("{\n.reg .b32 n;\nneg.f16x2 n, %1;\nfma.rn.f16x2 %0, n, %2, %3;\n}" : "=r"(d) : "r"(a), "r"(b), "r"(c));
    return d;
}
__device__ __forceinline__ uint32_t hadd(uint32_t a, uint32_t b) { uint32_t d; asm("add.rn.f16x2 %0, %1, %2;" : "=r"(d) : "r"(a), "r"(b)); return d; }
__device__ __forceinline__ uint32_t hsub(uint32_t a, uint32_t b) { uint32_t d; asm("sub.rn.f16x2 %0, %1, %2;" : "=r"(d) : "r"(a), "r"(b)); return d; }
__device__ __forceinline__ uint4 ldg_tab(int tab, int t) { return ldg128((const uint4*)c_fft + t + tab * 128); }
__device__ __forceinline__ uint32_t u4(const uint4& v, int i) { return i == 0 ? v.x : i == 1 ? v.y : i == 2 ? v.z : v.w; }
struct cpair { uint32_t r, i; };
__device__ __forceinline__ cpair pmul(cpair p, uint32_t z) {
    const __half2 zv = *reinterpret_cast<const __half2*>(&z), pr = *reinterpret_cast<const __half2*>(&p.r), pi = *reinterpret_cast<const __half2*>(&p.i);
    const __half2 zr = __low2half2(zv), zi = __high2half2(zv);
    const __half2 a = __hfma2(__hneg2(pi), zi, __hmul2(pr, zr)), b = __hfma2(pi, zr, __hmul2(pr, zi));
    return {*reinterpret_cast<const uint32_t*>(&a), *reinterpret_cast<const uint32_t*>(&b)};
}
__device__ __forceinline__ uint32_t packz(cplx z) { return pack2h(z.r, z.i); }
__device__ __forceinline__ void wgmma_kg(float (&d)[24], uint64_t da, uint64_t db, int scale_d) {
    asm volatile("{\n.reg .pred p;\nsetp.ne.b32 p, %26, 0;\n"
                 "wgmma.mma_async.sync.aligned.m64n48k16.f32.f16.f16 "
                 "{%0,%1,%2,%3,%4,%5,%6,%7,%8,%9,%10,%11,%12,%13,%14,%15,%16,%17,%18,%19,%20,%21,%22,%23}, %24, %25, p, 1, 1, 1, 1;\n}\n"
                 : "+f"(d[0]), "+f"(d[1]), "+f"(d[2]), "+f"(d[3]), "+f"(d[4]), "+f"(d[5]), "+f"(d[6]), "+f"(d[7]), "+f"(d[8]), "+f"(d[9]),
                   "+f"(d[10]), "+f"(d[11]), "+f"(d[12]), "+f"(d[13]), "+f"(d[14]), "+f"(d[15]), "+f"(d[16]), "+f"(d[17]), "+f"(d[18]), "+f"(d[19]),
                   "+f"(d[20]), "+f"(d[21]), "+f"(d[22]), "+f"(d[23])
                 : "l"(da), "l"(db), "r"(scale_d));
}

struct SsmParams { const bf16 *lar, *aim, *cre, *cim, *logdt, *dskip; const unsigned* epoch; };
constexpr int KG_TABLES = 6 * 16384, KG_RES = 1664;
struct KgShared { uint32_t kmax[6], kexp[6]; float cinv[6], tap0[6]; };
#define KS(f, i) (ks + (uint32_t)offsetof(KgShared, f) + 4 * (i))
struct KgParams { uint32_t l[3], a[3], r[3], i[3], dt, ds; };

__device__ __forceinline__ int cta_channel(int bx, int i) { return i < 2 ? 2 * bx + i : i < 4 ? 382 + 2 * bx + i : 256 + bx; }
__device__ __forceinline__ bool kg_is_hi(int warp) { return ((warp >> 1) ^ (warp >> 2)) & 1; }
__device__ __forceinline__ void kgen_load(KgParams& kp, int bx, int warp, int lane, const SsmParams& sp) {
    const int d = cta_channel(bx, 2 * (warp >> 2) + (warp & 1)), idx = d * (NMODE / 2) + lane;
    const bf16 *pr = kg_is_hi(warp) ? sp.cre : sp.lar, *pi = kg_is_hi(warp) ? sp.cim : sp.aim;
    kp.dt = __ldg((const uint16_t*)sp.logdt + d);
#pragma unroll
    for (int j = 0; j < 3; j++) {
        kp.l[j] = __ldg((const uint32_t*)sp.lar + idx + 32 * j); kp.a[j] = __ldg((const uint32_t*)sp.aim + idx + 32 * j);
        kp.r[j] = __ldg((const uint32_t*)pr + idx + 32 * j); kp.i[j] = __ldg((const uint32_t*)pi + idx + 32 * j);
    }
    kp.ds = __ldg((const uint16_t*)sp.dskip + cta_channel(bx, warp >> 1));
}

struct KgAnchors { uint32_t v[8]; };
__device__ __forceinline__ KgAnchors kg_anchor_lo(const KgParams& kp, uint32_t sel, float dt) {
    auto B = [&](uint32_t v) { return __uint_as_float(__byte_perm(v, 0u, sel)); };
    const float arl = -rbf(ex2(B(kp.l[0]) * 1.4426950408889634f)) * dt * 1.4426950408889634f, ai = B(kp.a[0]) * dt;
    const cplx z8 = cexp_p(arl, ai, 8.f), z16 = csq(z8), z24 = cmul(z16, z8), z32 = csq(z16), z64 = csq(z32), z128 = csq(z64), z192 = cmul(z128, z64);
    return {{pack2h(1.f, z8.r), pack2h(0.f, z8.i), pack2h(z16.r, z24.r), pack2h(z16.i, z24.i), packz(z32), packz(z64), packz(z128), packz(z192)}};
}
__device__ __forceinline__ KgAnchors kg_anchor_hi(const KgParams& kp, uint32_t sel, float dt, float cs) {
    auto B = [&](uint32_t v) { return __uint_as_float(__byte_perm(v, 0u, sel)); };
    const float arl = -rbf(ex2(B(kp.l[0]) * 1.4426950408889634f)) * dt * 1.4426950408889634f, ai = B(kp.a[0]) * dt;
    const cplx z1 = cexp_p(arl, -ai, 1.f), z2 = csq(z1), z4 = csq(z2), z256 = cexp_p(arl, -ai, 256.f), z512 = csq(z256), z1024 = csq(z512);
    const cplx H0 = {B(kp.r[0]) * cs, -B(kp.i[0]) * cs}, H4 = cmul(H0, z4);
    return {{pack2h(H0.r, H4.r), pack2h(H0.i, H4.i), packz(z1), packz(z2), packz(z256), packz(z512), packz(z1024), 0u}};
}

template <class Idle>
__device__ __forceinline__ void kgen_tables(KgParams& kp, uint32_t scr, uint32_t dump, uint32_t ks, int warp, int lane, Idle idle TS_ARG) {
    const int wg = warp >> 2, half = warp & 1, sw = lane & 7;
    const bool hi = kg_is_hi(warp);
    TS(23);
    const float dt = rbf(ex2(bf_lo(kp.dt) * 1.4426950408889634f));
    uint32_t sel = (wg == 2 && half) ? 0x3244u : 0x1044u;
    float cs = 0.f;
    KgAnchors an;
    if (hi) {
        uint32_t m = 0;
#pragma unroll
        for (int j = 0; j < 3; j++) m = __vmaxu2(m, __vmaxu2(kp.r[j] & 0x7FFF7FFFu, kp.i[j] & 0x7FFF7FFFu));
        m = __reduce_max_sync(~0u, max(m << 16, m & 0xFFFF0000u));
        const uint32_t e = min(max(__float_as_uint(2.f * dt * __uint_as_float(m)) >> 23, 2u), 252u);
        cs = 2.f * dt * __uint_as_float((253u - e) << 23);
        if (lane == 0) { sts32(KS(cinv, 2 * wg + half), (e + 1u) << 23); sts32(KS(kmax, 2 * wg + half), 0u); }
        an = kg_anchor_hi(kp, sel, dt, cs);
    } else {
        an = kg_anchor_lo(kp, sel, dt);
    }
    float acc[24];
#pragma unroll
    for (int i = 0; i < 24; i++) acc[i] = 0.f;
    uint32_t tb = scr + 2 * wg * 16384 + lane * 128;
    uint64_t da = mkdesc(scr + 2 * wg * 16384, 4096, 1024, 1);
    int flip = 16384;
#pragma unroll 1
    for (int c = wg == 2 ? 1 : 0, step = wg == 2 ? 2 : 1; c < 6; c += step) {
        if (wg < 2) sel ^= 0x2200u;
        if (!hi) {
            if (c & 1) { kp.l[0] = kp.l[1]; kp.l[1] = kp.l[2]; kp.a[0] = kp.a[1]; kp.a[1] = kp.a[2]; }
            cpair p[4];
            p[0] = {an.v[0], an.v[1]}; p[1] = {an.v[2], an.v[3]};
            p[2] = pmul(p[0], an.v[4]); p[3] = pmul(p[1], an.v[4]);
#pragma unroll
            for (int j = 0; j < 4; j++) {
                cpair v[4];
#pragma unroll
                for (int i = 0; i < 4; i++) v[i] = j ? pmul(p[i], an.v[4 + j]) : p[i];
                const uint32_t a = tb + (((4 * half + j) ^ sw) << 4);
                sts128(a, make_uint4(v[0].r, v[1].r, v[2].r, v[3].r));
                sts128(a + 4096, make_uint4(v[0].i, v[1].i, v[2].i, v[3].i));
            }
            an = kg_anchor_lo(kp, sel, dt);
        } else {
            if (c & 1) {
#pragma unroll
                for (int j = 0; j < 2; j++) { kp.l[j] = kp.l[j + 1]; kp.a[j] = kp.a[j + 1]; kp.r[j] = kp.r[j + 1]; kp.i[j] = kp.i[j + 1]; }
            }
            const uint32_t h1 = an.v[2], h2 = an.v[3], h256 = an.v[4], h512 = an.v[5], h1024 = an.v[6];
            cpair p[11];
            p[0] = {an.v[0], an.v[1]};
            p[1] = pmul(p[0], h2); p[2] = pmul(p[0], h1); p[3] = pmul(p[1], h1);
            p[4] = pmul(p[0], h256); p[5] = pmul(p[1], h256); p[6] = pmul(p[0], h512); p[7] = pmul(p[4], h512);
            p[8] = pmul({__byte_perm(p[0].r, p[4].r, 0x5410), __byte_perm(p[0].i, p[4].i, 0x5410)}, h1024);
            p[9] = pmul(p[8], h512); p[10] = pmul(p[8], h1024);
#pragma unroll
            for (int j = 0; j < 3; j++) {
                const uint32_t a = tb + 8192 + (((3 * half + j) ^ sw) << 4);
                sts128(a, make_uint4(p[4 * j].r, p[4 * j + 1].r, p[4 * j + 2].r, p[j < 2 ? 4 * j + 3 : 10].r));
                sts128(a + 4096, make_uint4(p[4 * j].i, p[4 * j + 1].i, p[4 * j + 2].i, p[j < 2 ? 4 * j + 3 : 10].i));
            }
            an = kg_anchor_hi(kp, sel, dt, cs);
        }
        if (c == 0) TS(24);
        if (c == 3) TS(25);
        fence_async_smem();
        wg_wait<0>();
        named_bar(5 + wg, 128);
        wg_fence();
#pragma unroll
        for (int k = 0; k < 4; k++) wgmma_kg(acc, da + k * 128, da + 512 + k * 128, 1);
        wg_commit();
        tb += flip; da += flip >> 4; flip = -flip;
    }
    const bool up = warp & 2;
    const int r = 2 * wg + up, lo0 = 16 * half + (lane >> 2);
    const uint32_t o = dump + r * KG_RES + lo0 * 52 + 4 * (lane & 3);
    const float ci = __uint_as_float(lds32(KS(cinv, r)));
    const float ds = warp <= 8 ? bf_lo(kp.ds) : 0.f;
    TS(26);
    idle();
    wg_wait<0>();
    float v[12], m = 0.f;
#pragma unroll
    for (int j = 0; j < 12; j++) { v[j] = up ? acc[12 + j] : acc[j]; m = fmaxf(m, fabsf(v[j])); }
#pragma unroll
    for (int j = 0; j < 6; j++) sts32(o + (j & 1) * 416 + (j >> 1) * 16, pack2h(v[2 * j], v[2 * j + 1]));
    const uint32_t mm = __reduce_max_sync(~0u, __float_as_uint(m));
    if (lane == 0) {
        asm volatile("red.shared.max.u32 [%0], %1;" ::"r"(KS(kmax, r)), "r"(mm) : "memory");
        if (!half) sts32(KS(tap0, r), __float_as_uint(fmaf(ci, v[0], ds)));
    }
}
#define F_STAG 4
__device__ __forceinline__ void wgmma_h64_rs(uint32_t (&d)[16], const uint4& a, uint64_t db, int scale_d) {
    asm volatile("{\n.reg .pred p;\nsetp.ne.b32 p, %21, 0;\n"
                 "wgmma.mma_async.sync.aligned.m64n64k16.f16.f16.f16 {%0,%1,%2,%3,%4,%5,%6,%7,%8,%9,%10,%11,%12,%13,%14,%15}, {%16,%17,%18,%19}, %20, p, 1, 1, 1;\n}\n"
                 : "+r"(d[0]), "+r"(d[1]), "+r"(d[2]), "+r"(d[3]), "+r"(d[4]), "+r"(d[5]), "+r"(d[6]), "+r"(d[7]), "+r"(d[8]), "+r"(d[9]),
                   "+r"(d[10]), "+r"(d[11]), "+r"(d[12]), "+r"(d[13]), "+r"(d[14]), "+r"(d[15])
                 : "r"(a.x), "r"(a.y), "r"(a.z), "r"(a.w), "l"(db), "r"(scale_d));
}
template <int TB>
__device__ __forceinline__ void wgmma_h32_rs(uint32_t (&d)[8], const uint4& a, uint64_t db, int scale_d) {
    asm volatile("{\n.reg .pred p;\nsetp.ne.b32 p, %13, 0;\n"
                 "wgmma.mma_async.sync.aligned.m64n32k16.f16.f16.f16 {%0,%1,%2,%3,%4,%5,%6,%7}, {%8,%9,%10,%11}, %12, p, 1, 1, %14;\n}\n"
                 : "+r"(d[0]), "+r"(d[1]), "+r"(d[2]), "+r"(d[3]), "+r"(d[4]), "+r"(d[5]), "+r"(d[6]), "+r"(d[7])
                 : "r"(a.x), "r"(a.y), "r"(a.z), "r"(a.w), "l"(db), "r"(scale_d), "n"(TB));
}
__device__ __forceinline__ void wgmma_s1(uint32_t (&d)[16], const uint4& a, uint64_t db, int scale_d) { wgmma_h64_rs(d, a, db, scale_d); }
__device__ __forceinline__ void wgmma_s1(uint32_t (&d)[8], const uint4& a, uint64_t db, int scale_d) { wgmma_h32_rs<1>(d, a, db, scale_d); }
__device__ __forceinline__ void wgmma_s4(float (&d)[32], const uint4& a, uint64_t db, uint32_t meta, int scale_d) {
    asm volatile("{\n.reg .pred p;\nsetp.ne.b32 p, %38, 0;\n"
                 "wgmma.mma_async.sp.sync.aligned.m64n64k32.f32.f16.f16 {%0,%1,%2,%3,%4,%5,%6,%7,%8,%9,%10,%11,%12,%13,%14,%15,%16,%17,%18,%19,%20,%21,%22,%23,%24,%25,%26,%27,%28,%29,%30,%31}, {%32,%33,%34,%35}, %36, %37, 0, p, 1, 1, 1;\n}\n"
                 : "+f"(d[0]), "+f"(d[1]), "+f"(d[2]), "+f"(d[3]), "+f"(d[4]), "+f"(d[5]), "+f"(d[6]), "+f"(d[7]), "+f"(d[8]), "+f"(d[9]), "+f"(d[10]), "+f"(d[11]), "+f"(d[12]), "+f"(d[13]), "+f"(d[14]), "+f"(d[15]), "+f"(d[16]), "+f"(d[17]), "+f"(d[18]), "+f"(d[19]), "+f"(d[20]), "+f"(d[21]), "+f"(d[22]), "+f"(d[23]), "+f"(d[24]), "+f"(d[25]), "+f"(d[26]), "+f"(d[27]), "+f"(d[28]), "+f"(d[29]), "+f"(d[30]), "+f"(d[31])
                 : "r"(a.x), "r"(a.y), "r"(a.z), "r"(a.w), "l"(db), "r"(meta), "r"(scale_d));
}
__device__ __forceinline__ void wgmma_s4(float (&d)[16], const uint4& a, uint64_t db, uint32_t meta, int scale_d) {
    asm volatile("{\n.reg .pred p;\nsetp.ne.b32 p, %22, 0;\n"
                 "wgmma.mma_async.sp.sync.aligned.m64n32k32.f32.f16.f16 {%0,%1,%2,%3,%4,%5,%6,%7,%8,%9,%10,%11,%12,%13,%14,%15}, {%16,%17,%18,%19}, %20, %21, 0, p, 1, 1, 1;\n}\n"
                 : "+f"(d[0]), "+f"(d[1]), "+f"(d[2]), "+f"(d[3]), "+f"(d[4]), "+f"(d[5]), "+f"(d[6]), "+f"(d[7]), "+f"(d[8]), "+f"(d[9]), "+f"(d[10]), "+f"(d[11]), "+f"(d[12]), "+f"(d[13]), "+f"(d[14]), "+f"(d[15])
                 : "r"(a.x), "r"(a.y), "r"(a.z), "r"(a.w), "l"(db), "r"(meta), "r"(scale_d));
}

__device__ __forceinline__ uint32_t& u4r(uint4& v, int i) { return i == 0 ? v.x : i == 1 ? v.y : i == 2 ? v.z : v.w; }

template <int NC>
__device__ __forceinline__ void fft_stage(const uint32_t (&u)[2][4], int c, uint32_t eo, int w, int lane) {
    const int mi = lane >> 3, mj = lane & 7;
    const uint32_t a = eo + (8 * w + mj) * 128 + (((4 * c + mi) ^ mj) << 4);
    stsm_x4(a, hadd(u[0][0], u[1][0]), hadd(u[0][1], u[1][1]), hadd(u[0][2], u[1][2]), hadd(u[0][3], u[1][3]));
    stsm_x4(NC == 2 ? a + 4096 : a ^ 64, hsub(u[0][0], u[1][0]), hsub(u[0][1], u[1][1]), hsub(u[0][2], u[1][2]), hsub(u[0][3], u[1][3]));
}
template <int NC>
__device__ __forceinline__ void kernel_stage(const uint4 (&ko)[2], uint32_t kt, uint32_t ks, int r, uint32_t eo, int w, int lane) {
    uint32_t u[2][2][4], sc[NC], t0[NC];
#pragma unroll
    for (int c = 0; c < NC; c++) {
        auto L = [](uint32_t a) { return __uint_as_float(lds32(a)); };
        const float ci = L(KS(cinv, r + c)), k0 = L(KS(tap0, r + c)) + (NC == 1 ? L(KS(tap0, r + 1)) : 0.f);
        const float mx = fmaxf(ci * (L(KS(kmax, r + c)) + (NC == 1 ? L(KS(kmax, r + 1)) : 0.f) + 0x1p-14f), fabsf(k0));
        const uint32_t e = min(max(__float_as_uint(mx) >> 23, 4u), 250u);
        const float s = __uint_as_float((253u - e) << 23), f = s * ci;
        if (w == 0 && lane == 0) sts32(KS(kexp, r + c), e);
        sc[c] = pack2h(f, f); t0[c] = pack2h(k0 * s, 0.f);
    }
#pragma unroll
    for (int h = 0; h < 2; h++)
#pragma unroll
        for (int j = 0; j < 4; j++) {
            const uint32_t a0 = kt + (u4(ko[h], j) & 0xFFFF), a1 = kt + (u4(ko[h], j) >> 16);
#pragma unroll
            for (int c = 0; c < 2; c++)
                asm volatile("{\n.reg .b16 a, b;\nld.shared.b16 a, [%1];\nld.shared.b16 b, [%2];\nmov.b32 %0, {a, b};\n}"
                             : "=r"(u[c][h][j]) : "r"(a0 + c * KG_RES), "r"(a1 + c * KG_RES) : "memory");
            if (NC == 1) u[0][h][j] = hadd(u[0][h][j], u[1][h][j]);
#pragma unroll
            for (int c = 0; c < NC; c++) {
                u[c][h][j] = hmul(u[c][h][j], sc[c]);
                if (h + j == 0 && w == 0 && lane == 0) u[c][0][0] = __byte_perm(t0[c], u[c][0][0], 0x7610);
            }
        }
#pragma unroll
    for (int c = 0; c < NC; c++) fft_stage<NC>(u[c], c, eo, w, lane);
}

template <int NC, bool SHEAR, class Mid>
__device__ __forceinline__ void fft_forward(const uint4 (&a1)[4], const uint4 (&tw)[4], uint32_t eo, uint32_t s2, uint32_t (&X)[NC][2][8], Mid mid) {
    uint32_t dr[8 * NC], di[8 * NC];
    const uint64_t de = mkdesc(eo, 4096, 1024, 1), d2 = mkdesc(s2, 16, 1024, 1);
    wg_fence();
    wgmma_s1(dr, a1[0], de, 0);
    wgmma_s1(di, a1[2], de + (NC == 2 ? 256 : 4), 0);
    wgmma_s1(dr, a1[1], de + 128, 1);
    wgmma_s1(di, a1[3], de + (NC == 2 ? 384 : 132), 1);
    wg_commit();
    mid();
    wg_wait<0>();
#pragma unroll
    for (int c = 0; c < NC; c++) {
        uint4 zr[2], zi[2];
#pragma unroll
        for (int p = 0; p < 2; p++)
#pragma unroll
            for (int i = 0; i < 4; i++) {
                const uint32_t r = dr[8 * c + 4 * p + i], m = di[8 * c + 4 * p + i], tr = u4(tw[p], i), ti = u4(tw[2 + p], i);
                if (SHEAR) {
                    const uint32_t r1 = hfma(tr, m, r), m1 = hfma(ti, r1, m);
                    u4r(zr[p], i) = hfma(tr, m1, r1); u4r(zi[p], i) = m1;
                } else {
                    u4r(zr[p], i) = hfms(m, ti, hmul(r, tr));
                    u4r(zi[p], i) = hfma(m, tr, hmul(r, ti));
                }
            }
        wg_fence();
        wgmma_h32_rs<0>(X[c][0], zi[0], d2 + 2, 0);
        wgmma_h32_rs<0>(X[c][1], zi[1], d2 + 6, 0);
        wgmma_h32_rs<0>(X[c][0], zr[0], d2, 1);
        wgmma_h32_rs<0>(X[c][1], zr[1], d2 + 4, 1);
        wg_commit();
    }
}

template <int NC, class Idle, class Staged>
__device__ __forceinline__ void conv_wg(int ch0, int layer, uint32_t eo, uint32_t zb, uint32_t s23, uint32_t kexp, uint32_t epoch, uint32_t st, uint32_t sbar, uint32_t fbar,
                                        int warp, int lane, uint4 (&a1)[4], uint4 (&tw)[4], Idle idle, Staged staged TS_ARG) {
    const int wg = warp >> 2, w = warp & 3, t = 32 * w + lane, mi = lane >> 3, mj = lane & 7;
    auto F = [](uint32_t x) { return __uint_as_float(x); };
    uint32_t KH[NC][2][8];
    TS(2);
    fft_forward<NC, false>(a1, tw, eo, s23, KH, [] {});
    named_bar(1 + wg, 128);
    uint4 a4[4];
#pragma unroll
    for (int i = 0; i < 4; i++) if (NC == 2) { tw[i] = ldg_tab(4 + i, t); a4[i] = ldg_tab(12 + i, t); }
    wg_wait<0>();
    TS(4);
    idle();
    uint2 x[NC][2][2];
    const uint32_t ra[2] = {4u * t, 4u * (t ^ 252)};
    auto stats = [&] {
        uint4 s[8];
        TS(1);
#pragma unroll
        for (int i = 0; i < 8; i++) s[i] = make_uint4(layer, 0, 0, 0);
        int spin = 0;
        uint32_t bad;
        do {
            bad = 0;
#pragma unroll
            for (int i = 0; i < 8; i++)
                if (miss(0, s[i].x, layer ^ 1) & 1u) s[i] = ld_ll4((const uint4*)(g_fs[0] + ra[i >> 2] + (SEQ * (i & 1) + 1024 * ((i >> 1) & 1))));
#pragma unroll
            for (int i = 0; i < 8; i++) bad = miss(bad, s[i].x, layer ^ 1);
        } while ((bad & 1u) && ++spin < (1 << 18));
#pragma unroll
        for (int i = 0; i < 8; i++) sts128(st + i * 2048 + t * 16, s[i]);
        __syncwarp();
        if (lane == 0) mbar_arrive(sbar + 8 * w);
        TS(14);
    };
    {
        const int tile = ((2 * w + (lane & 1)) ^ ((lane & 2) ? 15 : 0)) + 4 * (lane & 4);
        const bf16* pp = g_x1T + (uint32_t)(ch0 + NC - 1) * XP + 64 * tile + 60;
        uint32_t v;
        int spin = 0;
        do { asm volatile("ld.relaxed.gpu.global.u32 %0, [%1];" : "=r"(v) : "l"(pp) : "memory"); } while (__any_sync(~0u, ~(v ^ layer) & 1u) && ++spin < HINT_SPINS);
    }
    TS(5);
    auto xload = [&](int i) {
        const unsigned long long v = ld_ll((const unsigned long long*)(g_x1T + (uint32_t)ch0 * XP + ra[(i >> 1) & 1] + ((i >> 2) * XP + 1024 * (i & 1))));
        x[i >> 2][(i >> 1) & 1][i & 1] = make_uint2((uint32_t)v, (uint32_t)(v >> 32));
    };
#pragma unroll
    for (int i = 0; i < 4 * NC; i++) xload(i);
    TS(6);
    if (NC == 1) stats();
    for (int spin = 0; spin < (1 << 18); spin++) {
        uint32_t bad = 0;
#pragma unroll
        for (int i = 0; i < 4 * NC; i++) bad = miss(bad, x[i >> 2][(i >> 1) & 1][i & 1].x, layer ^ 1);
        if (!(bad & 1u)) break;
#pragma unroll
        for (int i = 0; i < 4 * NC; i++) if (miss(0, x[i >> 2][(i >> 1) & 1][i & 1].x, layer ^ 1) & 1u) xload(i);
    }
    __syncwarp();
#pragma unroll
    for (int i = 0; i < 4; i++) if (NC == 1) { tw[i] = ldg_tab(4 + i, t); a4[i] = ldg_tab(12 + i, t); }
    TS(26);
    if (NC == 2) mbar_wait(sbar + 8 * w, 0);
    staged();
    {
        uint4 s[2][2][2];
        uint32_t u[NC][2][4];
#pragma unroll
        for (int h = 0; h < 2; h++) {
            if (NC == 1 || h == 0) {
#pragma unroll
                for (int i = 4 * h; i < (NC == 1 ? 4 * h + 4 : 8); i++) s[i >> 2][(i >> 1) & 1][i & 1] = lds128(st + i * 2048 + t * 16);
            }
            if (h == 0) TS(7);
#pragma unroll
            for (int c = 0; c < NC; c++)
#pragma unroll
                for (int j = 0; j < 4; j++) {
                    const uint4 &a = s[h][j >> 1][0], &b = s[h][j >> 1][1];
                    const uint32_t xv = (j & 1) ? x[c][h][j >> 1].y : x[c][h][j >> 1].x;
                    u[c][h][j] = pack2h(fmaf(bf_lo(xv), F(u4(a, 2 * (j & 1))), F(u4(b, 2 * (j & 1)))), fmaf(bf_hi(xv), F(u4(a, 2 * (j & 1) + 1)), F(u4(b, 2 * (j & 1) + 1))));
                }
        }
#pragma unroll
        for (int c = 0; c < NC; c++) fft_stage<NC>(u[c], c, eo, w, lane);
    }
    TS(8);
    fence_async_smem();
    TS(9);
    named_bar(1 + wg, 128);
    uint32_t X[NC][2][8], Y[NC][2][8];
    uint32_t oscale[NC];
    fft_forward<NC, true>(a1, tw, eo, s23, X, [&] {
#pragma unroll
        for (int c = 0; c < NC; c++) oscale[c] = (lds32(kexp + 4 * c) + 3u) * 0x00800080u;
        if (layer) {
#pragma unroll
            for (int i = 0; i < 4 * NC; i++) asm volatile("mov.b32 %0, 0;\nmov.b32 %1, 0;" : "=r"(x[i >> 2][(i >> 1) & 1][i & 1].x), "=r"(x[i >> 2][(i >> 1) & 1][i & 1].y));
        }
        if (NC == 2 && wg == 1 && lane == 0) mbar_arrive(fbar);
        TS(3); if (F_STAG >= 2 && NC == 2 && wg == 1) named_bar(10 + w, 64); });
    if (F_STAG == 2 && NC == 2 && wg == 0) asm volatile("bar.arrive %0, 64;" ::"r"(10 + w) : "memory");
    TS(10);
    const uint64_t d3 = mkdesc(s23 + 4096, 16, 1024, 1);
#pragma unroll
    for (int c = 0; c < NC; c++) {
        wg_wait<NC - 1>();
        TS(11 + c);
        uint4 pr[2], pi[2];
#pragma unroll
        for (int i = 0; i < 4; i++) {
            const uint32_t er = X[c][0][i], ei = X[c][0][4 + i], orr = X[c][1][i], oi = X[c][1][4 + i];
            const uint32_t ar = KH[c][0][i], ai = KH[c][0][4 + i], br = KH[c][1][i], bi = KH[c][1][4 + i];
            u4r(pr[0], i) = hfms(bi, oi, hfma(br, orr, hfms(ai, ei, hmul(ar, er))));
            u4r(pi[0], i) = hfma(bi, orr, hfma(br, oi, hfma(ai, er, hmul(ar, ei))));
            u4r(pr[1], i) = hfms(ai, oi, hfma(ar, orr, hfms(bi, ei, hmul(br, er))));
            u4r(pi[1], i) = hfma(ai, orr, hfma(ar, oi, hfma(bi, er, hmul(br, ei))));
        }
        if (F_STAG == 3 + c && NC == 2 && wg == 0) asm volatile("bar.arrive %0, 64;" ::"r"(10 + w), "r"(pr[0].x ^ pr[1].w ^ pi[0].y ^ pi[1].z) : "memory");
        wg_fence();
        wgmma_h32_rs<0>(Y[c][0], pr[0], d3, 0);
        wgmma_h32_rs<0>(Y[c][1], pr[1], d3 + 4, 0);
        wgmma_h32_rs<0>(Y[c][0], pi[0], d3 + 2, 1);
        wgmma_h32_rs<0>(Y[c][1], pi[1], d3 + 6, 1);
        wg_commit();
    }
#pragma unroll
    for (int c = 0; c < NC; c++) {
        if (c + 1 < NC) wg_wait<1>(); else wg_wait<0>();
        TS(13 + c);
        uint32_t zr[2][4], zi[2][4];
#pragma unroll
        for (int p = 0; p < 2; p++)
#pragma unroll
            for (int i = 0; i < 4; i++) {
                const uint32_t r = Y[c][p][i], m = Y[c][p][4 + i], tr = u4(tw[p], i), ti = u4(tw[2 + p], i);
                const uint32_t r1 = hfms(tr, m, r), m1 = hfms(ti, r1, m);
                zr[i & 1][2 * p + (i >> 1)] = hfms(tr, m1, r1);
                zi[i & 1][2 * p + (i >> 1)] = m1;
            }
        const int kr = 4 * (mj >> 1) + (mj & 1) + 2 * (mj >> 2), ki = kr ^ 2;
#pragma unroll
        for (int h = 0; h < 2; h++) {
            const uint32_t a = zb + (2 * w + h) * 2048;
            stsm_x4(a + ki * 128 + (((4 * c + mi) ^ (ki & 7)) << 4), zi[h][0], zi[h][1], zi[h][2], zi[h][3]);
            stsm_x4(a + kr * 128 + (((4 * c + mi) ^ (kr & 7)) << 4), zr[h][0], zr[h][1], zr[h][2], zr[h][3]);
        }
    }
    TS(15);
    fence_async_smem();
    TS(16);
    named_bar(1 + wg, 128);
    TS(17);
    float acc[16 * NC];
    const uint64_t dz = mkdesc(zb, 4096, 1024, 1);
    wg_fence();
#pragma unroll
    for (int ks = 0; ks < 4; ks++) wgmma_s4(acc, a4[ks], dz + ks * 256, 0x44EEEE44u, ks > 0);
    wg_commit();
    const uint32_t fb = ~lds32(epoch);
    uint32_t mk[NC][2][4];
    const char* dst[2];
    {
        uint32_t l2;
        asm volatile("mov.u32 %0, %%laneid;" : "=r"(l2));
        const char* base = layer ? (const char*)g_of + (uint32_t)(ch0 / 80) * 327680u + (uint32_t)(ch0 % 80) * 256u : (const char*)g_x2T + (uint32_t)ch0 * (XP * 2u);
        const uint32_t k0 = layer ? 8 : (ch0 >> 1) & 3;
        uint32_t m0[2] = {k0 == 2 * (l2 & 3), k0 == 2 * (l2 & 3) + 1}, m1[2][2];
#pragma unroll
        for (int h = 0; h < 2; h++) {
            const uint32_t v = (32 * w + l2) ^ (h ? 252u : 0u);
            dst[h] = base + (layer ? (v >> 4) * 20480u + (v & 15u) * 16u : v * 8u);
            m1[h][0] = m0[0] | (~(v >> 3) & layer); m1[h][1] = m0[1] | ((v >> 3) & layer);
            asm volatile("" : "+l"(dst[h]), "+r"(m1[h][0]), "+r"(m1[h][1]), "+r"(m0[h]), "+r"(oscale[h % NC]));
        }
#pragma unroll
        for (int i = 0; i < 8 * NC; i++) {
            const int c = i >> 3, h = (i >> 2) & 1, j = i & 3;
            mk[c][h][j] = (j >> 1) == (NC == 2 ? c : ch0 & 1) ? m1[h][j & 1] : m0[j & 1];
            if (NC == 1) asm volatile("" : "+r"(mk[c][h][j]));
        }
        mbar_wait(sbar, 0);
    }
    auto mark = [&](uint32_t v, uint32_t m) { return (v & ~m) | (fb & m); };
    wg_wait<0>();
    TS(18);
#pragma unroll
    for (int c = 0; c < NC; c++) {
        uint32_t r[2][4];
#pragma unroll
        for (int j = 0; j < 4; j++) {
            const float* d = acc + 4 * (4 * c + j);
            const uint32_t y0 = pack2(d[0] + d[2], d[1] + d[3]), y1 = pack2(d[0] - d[2], d[1] - d[3]);
            asm("fma.rn.bf16x2 %0, %1, %2, %3;" : "=r"(r[0][j]) : "r"(y0), "r"(oscale[c]), "r"((j & 1) ? x[c][0][j >> 1].y : x[c][0][j >> 1].x));
            asm("fma.rn.bf16x2 %0, %1, %2, %3;" : "=r"(r[1][j]) : "r"(y1), "r"(oscale[c]), "r"((j & 1) ? x[c][1][j >> 1].y : x[c][1][j >> 1].x));
        }
#pragma unroll
        for (int h = 0; h < 2; h++)
            asm volatile("{\n.reg .pred p;\n.reg .b128 t;\n.reg .b64 a, b;\nsetp.ne.u32 p, %5, 0;\nmov.b64 a, {%1, %2};\nmov.b64 b, {%3, %4};\nmov.b128 t, {a, b};\n"
                         "@p st.relaxed.gpu.global.b128 [%0], t;\n@!p st.relaxed.gpu.global.b64 [%6], a;\n@!p st.relaxed.gpu.global.b64 [%6 + 2048], b;\n}"
                         ::"l"(dst[h] + c * 256), "r"(mark(r[h][0], mk[c][h][0])), "r"(mark(r[h][1], mk[c][h][1])), "r"(mark(r[h][2], mk[c][h][2])), "r"(mark(r[h][3], mk[c][h][3])), "r"(layer), "l"(dst[h] + c * XP * 2) : "memory");
    }
    if (layer == 0 && lane == 0) asm volatile("red.relaxed.gpu.global.add.u32 [%0], %1;" ::"l"(g_xcnt[ch0 >> 6][w]), "n"(NC) : "memory");
    TS(19);
}

#define R_CONS 192
#define K_CSUN 1
constexpr int K_CSU = K_CSUN;
#define G_MAP 1
constexpr int Q_SP = 4;
#define A_VLO 4
constexpr int Q_ST = 4;
constexpr int Q_AB = 16384, Q_BB = 30720, Q_SB = Q_AB + Q_BB;
constexpr int Q_EROW = 336;
constexpr int Q_ESLOT = 8 * Q_EROW;
constexpr int Q_EOFF = Q_ST * Q_SB;
constexpr int Q_KG = 2 * Q_SB;
static_assert(3 * Q_ESLOT <= 8192 && Q_KG + KG_TABLES <= Q_EOFF + 4096, "exchange slots, kernel generation");
constexpr int F_EO = Q_EOFF, F_S23 = F_EO + 2 * 8192 + 4096, Q_KDUMP = F_S23 + 8192;
constexpr int Q_MISC = Q_KDUMP + 6 * KG_RES;
__host__ __device__ constexpr int w_grp(int j) { return j ? 2 * Q_SB + 4096 + (j - 1) * 12800 : 0; }
constexpr int W_RES = Q_AB;
__device__ __forceinline__ int o_slot(int wg, int j) { return W_RES + wg * 10240 + (j & 3) * 20480; }
__device__ __forceinline__ int w_out(int wg) { return W_RES + (2 + 3 * wg) * 10240; }
static_assert(W_RES + 8 * 10240 == w_grp(1) && w_grp(7) + 12800 <= Q_EOFF && w_grp(4) <= 3 * Q_SB, "phase W layout");

constexpr int Q_WOT = Q_EOFF + 4096;

__device__ unsigned g_epoch;
__device__ __align__(1024) unsigned g_bar[4][16][32];
__device__ __align__(1024) uint4 g_wop[8][80][10][8];
__device__ __align__(1024) uint4 g_csp[8][16][96];
__device__ __align__(1024) uint4 g_stp[16][8][64];
__device__ __align__(1024) uint4 g_sp2[16][8][8][8];
__device__ __align__(1024) uint4 g_halo[128][2][5][32];

struct Bars { uint64_t full[Q_ST], empty[Q_ST], wfull, ex[7], res, qdone, prep, hdone, idx, fdone0, att[2], wfree, soon[2], fdone1, st[4], kfree, staged, xland[4], spec; };
constexpr int NBAR = sizeof(Bars) / 8;
struct OBars { uint64_t b[2][12]; };
struct Misc { float cs[240], mean[2][64], rstd[2][72]; Bars bar[2]; OBars ob; KgShared kg; uint32_t epoch, pad; };
#define MISC(f) (sb + Q_MISC + (uint32_t)offsetof(Misc, f))
constexpr int Q_SMEM = Q_MISC + sizeof(Misc) + TS_SMEM;
__host__ __device__ constexpr int bar_count(int i) {
#define BAR_IS(f) (i == offsetof(Bars, f) / 8)
    return (i >= 4 && i < 8) ? 16 : (i >= offsetof(Bars, att) / 8 && i < offsetof(Bars, st) / 8) ? 4 : (BAR_IS(qdone) || BAR_IS(fdone0)) ? 8 : BAR_IS(prep) ? 96 :
           BAR_IS(hdone) ? 6 : BAR_IS(kfree) ? 24 : BAR_IS(staged) ? 2 : 1;
}
__device__ __forceinline__ void grid_wait(const unsigned* c, int n, unsigned target, int lane) {
    const unsigned* p = c + 32 * min(lane, n - 1);
    unsigned v;
    int spin = 0;
    do { asm volatile("ld.relaxed.gpu.global.u32 %0, [%1];" : "=r"(v) : "l"(p) : "memory"); } while (!__all_sync(~0u, (int)(v - target) >= 0) && ++spin < (1 << 18));
    fence_acquire();
}
__device__ __forceinline__ void grid_arrive(unsigned* c) {
    fence_release();
    asm volatile("red.relaxed.gpu.global.add.u32 [%0], 1;" ::"l"(c) : "memory");
}

#define TMAP(n) ([] { const CUtensorMap* p_; asm volatile("{\n.reg .b64 t;\nmov.b64 t, fused_kernel_param_" #n ";\ncvta.param.u64 %0, t;\n}" : "=l"(p_)); return p_; }())
extern "C" __global__ void __launch_bounds__(384, 1)
fused_kernel(const SsmParams sp, const __grid_constant__ CUtensorMap mX0, const __grid_constant__ CUtensorMap mX1, const __grid_constant__ CUtensorMap mW,
             const __grid_constant__ CUtensorMap mWr,
             const __grid_constant__ CUtensorMap mRes0, const __grid_constant__ CUtensorMap mRes1, const __grid_constant__ CUtensorMap mOut,
             const __grid_constant__ CUtensorMap mWo, const __grid_constant__ CUtensorMap mFin, const __grid_constant__ CUtensorMap mResA) {
    extern __shared__ __align__(1024) char smraw[];
    const uint32_t sb = s2u(smraw);
    int tid, warp, lane, bx, rank, blk, hg, rot, c0;
    int role;
    {
        const int c = blockIdx.x >> 1, d = c - 41, r = d >= 21 ? 3 : d >= 14 ? 2 : d >= 7 ? 1 : 0;
        const int gp = c < 4 ? 0 : c <= 40 ? (c + 7) & 7 : d - 7 * r + 1;
        const int k = c < 4 ? c : c <= 40 ? (c >> 3) + (gp == 0 ? 3 : gp >= 3 && gp < 7 ? 0 : -1) : (gp >= 3 ? 5 : 4) + r;
        role = G_MAP == 1 ? 16 * k + 2 * gp + (blockIdx.x & 1) : G_MAP == 2 ? 16 * gp + 2 * k + (blockIdx.x & 1) : blockIdx.x;
    }
    auto indices = [&] {
        asm volatile("mov.u32 %0, %%tid.x;" : "=r"(tid));
        asm volatile("mov.u32 %0, %1;" : "=r"(bx) : "r"(role));
        warp = __shfl_sync(~0u, tid >> 5, 0); lane = tid & 31;
        rank = bx & 1; blk = bx & 15; hg = bx >> 4;
        const int u = ((blk >> 1) + hg) & 7;
        rot = (5 * u) >> 2; c0 = 16 * (u & 3);
    };
    indices();
    TS_DECL;
    TS_BEGIN;
#define EPOCH lds32(MISC(epoch))
    int layer = 0;
    uint32_t bars = MISC(bar);
#define BAR(f) (bars + (uint32_t)offsetof(Bars, f))
    auto chunk = [&](int it, int s0) {
        const int i = it < s0 ? it : it - 2;
        return (it >> 1) == (s0 >> 1) ? rot + (it & 1) : i < rot ? i : i + 2;
    };
    auto osrc_of = [&](int j) { return j == 0 ? hg : j - 1 < hg ? j - 1 : j; };
    auto issue_w = [&](uint32_t bb, int it, int lay) {
        const int half = rank;
        const int s = it & (Q_ST - 1);
        const uint32_t fb = bb + 8 * s, db = sb + s * Q_SB + Q_AB + half * 15360;
        const int k0 = chunk(it, Q_SP * lay) * 64 + half * 32;
#pragma unroll
        for (int p = 0; p < 3; p++) tma2d_mc(db + p * 4096, TMAP(3), p * DM + hg * 80, k0, fb, 3);
        tma3d_mc(db + 12288, TMAP(4), hg * 80 + 64, k0, 0, fb, 3);
    };
    auto issue_x = [&](int it) {
        const int s = it & (Q_ST - 1), kc = chunk(it, Q_SP * layer);
        mbar_expect(BAR(full) + 8 * s, Q_SB);
        tma3d(sb + s * Q_SB, TMAP(1) + layer, (layer ? blk : kc) * 64, (layer ? kc : blk) * 64, 0, BAR(full) + 8 * s);
    };
    {
        KgParams kp;
        const uint32_t epoch0 = ldg32(sp.epoch);
        kgen_load(kp, bx, warp, lane, sp);
        if (warp < 8) {
            cluster_arrive_relaxed();
        } else {
            if (elect_one()) {
                if (warp < 10) { prefetch_tmap(TMAP(3)); prefetch_tmap(TMAP(4)); } else prefetch_tmap(warp == 10 ? TMAP(1) : TMAP(8));
                const uint32_t b0 = bars + (warp >= 10 ? sizeof(Bars) : 0);
                if (warp & 1) {
#pragma unroll
                    for (int i = 0; i < NBAR / 2; i++) mbar_init(b0 + i * 8, bar_count(i));
                } else {
#pragma unroll
                    for (int i = NBAR / 2; i < NBAR; i++) mbar_init(b0 + i * 8, bar_count(i));
                }
                fence_mbar_init();
            }
            __syncwarp();
            cluster_arrive_relaxed();
            TS(29);
            cluster_wait();
            TS(27);
            if (elect_one()) {
                if (warp < 10) {
                    issue_w(BAR(full), warp - 8, 0);
                } else if (warp == 10) {
                    issue_x(0); issue_x(1);
                    prefetch_l2((const char*)c_fft + bx * (sizeof(c_fft) / 128), sizeof(c_fft) / 128);
                } else {
                    mbar_expect(BAR(idx), 8192 + 6400);
                    asm volatile("cp.async.bulk.tensor.4d.shared::cluster.global.mbarrier::complete_tx::bytes [%0], [%1, {0, 0, %3, %4}], [%2];"
                                 ::"r"(sb + Q_WOT), "l"(TMAP(8)), "r"(BAR(idx)), "r"(10 * hg), "r"(5 * blk) : "memory");
                    bulk_g2s(sb + F_S23, c_fft + 18 * 512, 8192, BAR(idx));
                }
            }
            __syncwarp();
            TS(30);
        }
        indices();
        kgen_tables(kp, sb + Q_KG, sb + Q_KDUMP, MISC(kg), warp, lane, [&] { if (warp < 8) cluster_wait(); } TS_PASS);
        __syncwarp();
        if (lane == 0) { mbar_arrive_cta(BAR(kfree), 0); mbar_arrive_cta(BAR(kfree), 1); }
        if (warp >= 8) {
            const int t2 = tid - 256;
            float csum[10];
            if (warp < 10 && elect_one()) {
#pragma unroll
                for (int i = 1; i < 12; i++) mbar_init(MISC(ob) + (warp - 8) * 96 + i * 8, i < 8 ? 1 : 4);
                fence_mbar_init();
            }
            __syncwarp();
            if (t2 == 0) sts32(MISC(epoch), epoch0);
            if (t2 < 64) stg128(&g_sp2[blk][hg][0][0] + t2, make_uint4(0, 0, 0, 0));
            if (t2 >= 64 && t2 < 80) stg128(&g_of[hg][blk][640 * ((t2 >> 3) & 1) + 8 * (73 + (t2 & 6)) + 6 + (t2 & 1)], make_uint4(epoch0, epoch0, epoch0, epoch0));
            if (t2 >= 120) stg128((uint4*)g_fs + 8 * bx + t2 - 120, make_uint4(0, 0, 0, 0));
#pragma unroll
            for (int i = 0; i < 2; i++)
                if (t2 + 128 * i < 192) stg128(g_x1T + (uint32_t)cta_channel(bx, 4 * i + 1 + 2 * (t2 >> 6)) * XP + 32 * (t2 & 62) + 48 + 8 * (t2 & 1), make_uint4(0, 0, 0, 0));
#pragma unroll
            for (int i = 0; i < 3; i++)
                if (t2 + 128 * i < 320) stg128(&g_halo[bx][0][0][0] + t2 + 128 * i, make_uint4(0, 0, 0, 0));
            named_bar(13, 128);
            if (warp > 8) {
                const int hw = warp - 9, mi = lane >> 3, mj = lane & 7;
                mbar_wait(BAR(idx), 0);
                if (hw == 2 && elect_one()) { bulk_s2g(&g_wop[hg][5 * blk], sb + Q_WOT, 6400); bulk_commit(); }
                __syncwarp();
                mbar_wait(BAR(full), 0);
                mbar_wait(BAR(full) + 8, 0);
#pragma unroll
                for (int f = 0; f < 10; f++) csum[f] = 0.f;
#pragma unroll K_CSU
                for (int G = 0; G < 5; G++) {
                    const int row = c0 + 40 * rank + 8 * G + mj;
                    const uint32_t b = sb + (row >> 6) * Q_SB + Q_AB + ((row >> 5) & 1) * 15360;
                    uint32_t r[10];
                    ldsm_x4_t(r[0], r[1], r[2], r[3], b + hw * 4096 + (row & 31) * 128 + ((mi ^ mj) << 4));
                    ldsm_x4_t(r[4], r[5], r[6], r[7], b + hw * 4096 + (row & 31) * 128 + (((4 + mi) ^ mj) << 4));
                    ldsm_x2_t(r[8], r[9], b + 12288 + hw * 1024 + (row & 31) * 32 + (((mi & 1) ^ (mj >> 2)) << 4));
#pragma unroll
                    for (int f = 0; f < 10; f++) csum[f] += bf_lo(r[f]) + bf_hi(r[f]);
                }
                const int q = lane & 3;
                float t[3];
#pragma unroll
                for (int j = 0; j < 3; j++) {
                    float v[4];
#pragma unroll
                    for (int k = 0; k < 4; k++) v[k] = 4 * j + k < 10 ? csum[4 * j + k] : 0.f;
                    const float a0 = ((q & 2) ? v[2] : v[0]) + __shfl_xor_sync(~0u, (q & 2) ? v[0] : v[2], 2);
                    const float a1 = ((q & 2) ? v[3] : v[1]) + __shfl_xor_sync(~0u, (q & 2) ? v[1] : v[3], 2);
                    t[j] = ((q & 1) ? a1 : a0) + __shfl_xor_sync(~0u, (q & 1) ? a0 : a1, 1);
                }
                st_ll4(&g_csp[hg][blk][tid - 288], ~EPOCH & 1u, __float_as_uint(t[0]), __float_as_uint(t[1]), __float_as_uint(t[2]));
            }
        }
        TS(1);
    }

    uint4 fa1[4], ftw[4];
    auto conv_tables = [&] {
#pragma unroll
        for (int i = 0; i < 4; i++) { fa1[i] = ldg_tab(i, tid & 127); ftw[i] = ldg_tab(8 + i, tid & 127); }
    };
    if (warp >= 8) {
    asm volatile("setmaxnreg.dec.sync.aligned.u32 %0;" ::"n"(504 - 2 * R_CONS));
#pragma unroll 1
    for (; layer < 2; layer++, bars += sizeof(Bars)) {
        indices();
        TS_PHASE(2 * layer);
        if (layer) {
            const int i = warp - 8, g = lane >> 2;
            const uint32_t eb = ~EPOCH, a = sb + i * Q_SB + g * 128 + (((2 * (lane & 3)) ^ g) << 4) + 2 * (g & 6);
            const unsigned* pp = g_xcnt[chunk(i, Q_SP)][(blk < 8 ? blk : 15 - blk) >> 1];
            mbar_wait(BAR(fdone0) - sizeof(Bars), 0);
            if (i == 3) mbar_wait(BAR(fdone1) - sizeof(Bars), 0);
            if (i == 3 && elect_one()) grid_arrive(g_bar[2][hg]);
            __syncwarp();
            uint32_t bad;
            int spin = 0;
            do { asm volatile("ld.relaxed.gpu.global.u32 %0, [%1];" : "=r"(bad) : "l"(pp) : "memory"); } while ((int)(bad + 64 * eb) < 0 && ++spin < HINT_SPINS);
            fence_async_global();
            TS(1);
            spin = 0;
            do {
                if (elect_one()) {
                    mbar_expect(BAR(xland) + 8 * i, Q_AB);
                    tma3d(sb + i * Q_SB, TMAP(2), blk * 64, chunk(i, Q_SP) * 64, 0, BAR(xland) + 8 * i);
                }
                __syncwarp();
                if (spin) COUNT(2);
                mbar_wait(BAR(xland) + 8 * i, spin & 1);
                bad = 0;
#pragma unroll
                for (int k = 0; k < 16; k++) bad = miss(bad, lds32(a + k * 1024), eb);
            } while (__any_sync(~0u, bad & 1u) && ++spin < (1 << 16));
            if (lane == 0) mbar_expect(BAR(full) + 8 * i, Q_BB);
            TS(9);
        }
        if (warp == 8) {
            if (layer) {
                grid_wait(g_bar[2][0], 8, 16 * (EPOCH + 1), lane);
                fence_async_global();
                TS(10);
            }
            if (elect_one()) {
#pragma unroll 1
                for (int it = 2 + 2 * layer; it < 10; it++) {
                    if (it >= Q_ST) mbar_wait(BAR(empty) + 8 * (it & (Q_ST - 1)), ((it >> 2) - 1) & 1);
                    else mbar_wait(BAR(kfree), 0);
                    if (it == Q_ST + Q_SP * layer) mbar_wait(BAR(hdone), 0);
                    issue_x(it);
                    issue_w(BAR(full), it, layer);
                    if (it == Q_SP + 1) mbar_arrive(BAR(spec));
                }
                { prefetch_tmap(TMAP(5) + layer); prefetch_tmap(TMAP(7)); prefetch_tmap(TMAP(10)); }
                if (layer == 0) { mbar_wait(BAR(prep), 0); fence_async_global(); }
#pragma unroll 1
                for (int n = 1; n < 9; n++) {
                    const int b = n >> 2, j = n & 7;
                    if (n == 1 || !(n & 3)) { mbar_wait(BAR(empty) + 8 * ((2 + b) & 3), b < 2); TS(11 + b); }
                    bulk_g2s_mc(sb + w_grp(j) + rank * 6400, &g_wop[hg][osrc_of(j) * 10 + rank * 5], 6400, BAR(wfull), 3);
                }
                mbar_expect(BAR(wfull), 8 * 12800);
                mbar_expect(BAR(res), 20480);
                if (layer) {
                    tma3d(sb + W_RES, TMAP(6), blk * 64, hg * 80, 0, BAR(res));
                } else {
#pragma unroll 1
                    for (int p = 0; p < 2; p++) {
                        tma3d(sb + W_RES + p * 10240, TMAP(10), hg * 80, blk * 64, p, BAR(res));
                        tma3d(sb + W_RES + p * 10240 + 8192, TMAP(5), hg * 80 + 64, blk * 64, p, BAR(res));
                    }
                }
            }
            __syncwarp();
        } else {
            const int ht = tid - 288, hw = warp - 9, mi = lane >> 3, mj = lane & 7, g = lane >> 2, q = lane & 3;
            auto F = [](uint32_t x) { return __uint_as_float(x); };
            auto U = [](float x) { return __float_as_uint(x); };
            const uint32_t lb = layer ^ 1, eb = ~EPOCH & 1u;
            if (layer) mbar_wait(BAR(spec), 0);
            mbar_wait(BAR(full), layer);
            mbar_wait(BAR(full) + 8, layer);
            if (ht == 0) TSX(2, 2);
            uint32_t xf[3][20];
#pragma unroll
            for (int i = 0; i < 3; i++) {
                const int tile = min(hw + 3 * i, 7);
#pragma unroll
                for (int k = 0; k < 5; k++) {
                    const int ch = c0 + 16 * k + 8 * (mi >> 1), tok = 16 * (tile & 3) + 8 * (mi & 1);
                    const uint32_t a = sb + (ch >> 6) * Q_SB + (tile >> 2) * 8192;
                    if (layer == 0) ldsm_x4(xf[i][4 * k], xf[i][4 * k + 1], xf[i][4 * k + 2], xf[i][4 * k + 3], a + (tok + mj) * 128 + ((((ch & 63) >> 3) ^ mj) << 4));
                    else ldsm_x4_t(xf[i][4 * k], xf[i][4 * k + 1], xf[i][4 * k + 2], xf[i][4 * k + 3], a + ((ch & 63) + mj) * 128 + (((tok >> 3) ^ mj) << 4));
                }
            }
            fence_async_smem();
            __syncwarp();
            if (lane == 0) { mbar_arrive_cta(BAR(hdone), 0); mbar_arrive_cta(BAR(hdone), 1); }
            if (ht == 0) TSX(2, 3);
            if (layer == 0) {
                if (hw == 2 && elect_one()) { bulk_wait(); fence_async_global(); grid_arrive(g_bar[3][hg]); }
                __syncwarp();
                mbar_wait(BAR(kfree), 0);
            }
            if (ht == 0) TSX(2, 8);
#pragma unroll 1
            for (int tile = hw; tile < 8; tile += 3) {
                float a[4] = {0.f, 0.f, 0.f, 0.f};
#pragma unroll
                for (int j = 0; j < 20; j++) {
                    const float lo = bf_lo(xf[0][j]), hi = bf_hi(xf[0][j]);
                    a[2 * (j & 1)] += lo + hi; a[2 * (j & 1) + 1] = fmaf(lo, lo, fmaf(hi, hi, a[2 * (j & 1) + 1]));
                    xf[0][j] = xf[1][j]; xf[1][j] = xf[2][j];
                }
#pragma unroll
                for (int j = 0; j < 4; j++) { a[j] += __shfl_xor_sync(~0u, a[j], 1); a[j] += __shfl_xor_sync(~0u, a[j], 2); }
                if (q == 0) st_ll4(&g_stp[blk][hg][8 * tile + g], (U(a[0]) & ~1u) | lb, U(a[1]), U(a[2]), U(a[3]));
            }
            if (ht == 0) TSX(2, 4);
            if (layer == 0) {
                float t[4] = {0.f, 0.f, 0.f, 0.f};
                uint4 v[16];
                int spin = 0;
                uint32_t bad;
                do {
                    bad = 0;
#pragma unroll
                    for (int j = 0; j < 16; j++) v[j] = ld_ll4(&g_csp[hg][j][ht]);
#pragma unroll
                    for (int j = 0; j < 16; j++) bad = miss(bad, v[j].x, eb);
                } while ((bad & 1u) && ++spin < (1 << 18));
#pragma unroll
                for (int j = 0; j < 16; j++) { t[0] += F(v[j].y); t[1] += F(v[j].z); t[2] += F(v[j].w); }
#pragma unroll
                for (int j = 0; j < 3; j++) if (q + 4 * j < 10) sts32(MISC(cs) + 4 * (80 * hw + 20 * (g >> 1) + 2 * (q + 4 * j) + (g & 1)), U(t[j]));
                if (hw == 2) grid_wait(g_bar[3][0], 8, 16 * (EPOCH + 1), lane);
            }
            if (ht == 0) TSX(2, 15);
            if (ht < 80) {
                const bool halo = ht >= 64;
                const int p = halo ? (ht >> 3) & 1 : ht >> 5, i = halo ? (ht & 7) - 8 : 8 + 2 * (ht & 24) + (ht & 7);
                const uint4* src = &g_stp[halo && blk ? blk - 1 : blk][0][halo ? 32 * p + 24 + (ht & 7) : ht];
                uint4 v[8];
                int spin = 0;
                uint32_t bad;
                do {
                    bad = 0;
#pragma unroll
                    for (int j = 0; j < 8; j++) v[j] = ld_ll4(src + 64 * j);
#pragma unroll
                    for (int j = 0; j < 8; j++) bad = miss(bad, v[j].x, lb);
                } while ((bad & 1u) && ++spin < (1 << 18));
                float t[4] = {0.f, 0.f, 0.f, 0.f};
#pragma unroll
                for (int j = 0; j < 8; j++) { t[0] += F(v[j].x); t[1] += F(v[j].y); t[2] += F(v[j].z); t[3] += F(v[j].w); }
                const uint32_t s0 = ln_finish_packed(t[0], t[1]), s1 = ln_finish_packed(t[2], t[3]);
                const uint32_t am = MISC(mean) + 4 * (64 * p + i), ar = MISC(rstd) + 4 * (72 * p + i);
                if (!halo) { sts32(am - 32, U(bf_hi(s0))); sts32(am, U(bf_hi(s1))); sts32(ar, U(frcp(bf_lo(s0)))); }
                sts32(ar + 32, U(frcp(bf_lo(s1))));
            }
            fence_acquire();
            mbar_arrive(BAR(prep));
            if (ht == 0) TSX(2, 5);
        }
        __syncwarp();
        indices();
        {
            const uint4 ko[2] = {ldg_tab(16, tid & 127), ldg_tab(17, tid & 127)};
            conv_tables();
            kernel_stage<1>(ko, sb + Q_KDUMP + 4 * KG_RES, MISC(kg), 4, sb + F_EO + 2 * 8192, warp & 3, lane);
            fence_async_smem();
        }
        {
            const int p = warp & 1;
            const uint32_t fb = EPOCH ^ layer ^ 1, ob = MISC(ob) + 96 * p;
            if (warp >= 10) {
                const uint32_t* pp = &g_of[osrc_of(1 + min(lane >> 2, 6))][blk][640 * p + 8 * (73 + 2 * (lane & 3)) + 7].x + 1 + 2 * (lane & 1);
                mbar_wait(BAR(qdone), 0);
                mbar_wait(BAR(att) + 8 * p, 0);
                const char* src = (const char*)&g_of[0][blk][640 * p];
                uint32_t late = ~0u, need = 15u, bar = ob + 8;
                int spin = 0;
#pragma unroll 1
                for (int j = 1; j < 8; j++, need <<= 4, bar += 8, src += 327680) {
                    while ((late & need) && ++spin < HINT_SPINS) {
                        uint32_t v;
                        asm volatile("ld.relaxed.gpu.global.u32 %0, [%1];" : "=r"(v) : "l"(pp) : "memory");
                        late = __ballot_sync(~0u, miss(0, v, fb) & 1u);
                        fence_async_global();
                    }
                    if (j == 1) TS(16);
                    if (j - 1 == hg) src += 327680;
                    if (j > 3) mbar_wait(bar + 32, layer);
                    if (elect_one()) { mbar_expect(bar, 10240); bulk_g2s(sb + o_slot(p, j), src, 10240, bar); }
                }
                __syncwarp();
                TS(17);
            }
        }
        TS_PHASE(2 * layer + 1);
        TS(0);
        indices();
        named_bar(3, 128);
        conv_wg<1>(cta_channel(bx, 4), layer, sb + F_EO + 2 * 8192, sb + 2 * Q_SB, sb + F_S23, MISC(kg.kexp) + 16, MISC(epoch), sb, BAR(st), 0,
                   warp, lane, fa1, ftw,
        [&] {
            if (warp == 9) {
                auto F = [](uint32_t x) { return __uint_as_float(x); };
                mbar_wait(BAR(soon) + 8 * (hg >> 2), 0);
                TS(23);
                const uint4* src = &g_sp2[blk][hg][0][0] + lane;
                uint4* dst = (uint4*)(g_fs[(lane >> 2) & 1] + 1024 * (hg >> 2) + 64 * blk + 16 * (hg & 3)) + (lane & 3);
                const bool up = lane & 8;
#pragma unroll 1
                for (int spin = 0; spin < (1 << 18); spin++) {
                    const uint4 a = ld_ll4(src), b = ld_ll4(src + 32);
                    const bool ok = !__any_sync(~0u, miss(miss(0, a.x, layer ^ 1), b.x, layer ^ 1) & 1u);
                    const float s0 = F(a.x) + F(b.x), q0 = F(a.y) + F(b.y), s1 = F(a.z) + F(b.z), q1 = F(a.w) + F(b.w);
                    float sm = (up ? s1 : s0) + __shfl_xor_sync(~0u, up ? s0 : s1, 8), sq = (up ? q1 : q0) + __shfl_xor_sync(~0u, up ? q0 : q1, 8);
                    sm += __shfl_xor_sync(~0u, sm, 16); sq += __shfl_xor_sync(~0u, sq, 16);
                    const float m = sm * (1.0f / DM), r = frsq(fmaxf(fmaf(sq, 1.0f / DM, fmaf(-m, m, 1e-5f)), 1e-5f));
                    const uint32_t v = __float_as_uint(lane & 16 ? -m * r : r);
                    const uint32_t v0 = __shfl_sync(~0u, v, 4 * lane), v1 = __shfl_sync(~0u, v, 4 * lane + 1), v2 = __shfl_sync(~0u, v, 4 * lane + 2), v3 = __shfl_sync(~0u, v, 4 * lane + 3);
                    if (ok && lane < 8) st_ll4(dst, (v0 & ~1u) | (layer ^ 1), v1, v2, v3);
                    if (ok) break;
                }
            }
            TS(25);
            mbar_wait(BAR(staged), 0);
        }, [&] {
            if (tid == 352) prefetch_tmap(layer ? TMAP(9) : TMAP(2));
        } TS_PASS);
        named_bar(3, 128);
        TS(20);
    }
    } else {
#pragma unroll 1
    for (; layer < 2; layer++, bars += sizeof(Bars)) {
    indices();
    TS_PHASE(2 * layer);
    const int wg = warp >> 2, w = warp & 3;
    const int mi = lane >> 3, mj = lane & 7, g = lane >> 2, q = lane & 3;
    TS(2);
    float acc[120];
#pragma unroll
    for (int i = 0; i < 120; i++) acc[i] = 0.f;
    auto release = [&](int it) {
        if (lane == 0) { mbar_arrive_cta(BAR(empty) + 8 * (it & (Q_ST - 1)), 0); mbar_arrive_cta(BAR(empty) + 8 * (it & (Q_ST - 1)), 1); }
    };
#pragma unroll 1
    for (int it = 0; it < 10; it++) {
        const int s = it & (Q_ST - 1);
        const uint32_t st = sb + s * Q_SB;
        mbar_wait(BAR(full) + 8 * (s), (it >> 2) & 1);
        if (it < 2) TS(3 + it);
        if (it == 6) TS(5);
        if (it == 9) TS(6);
        const uint64_t da = mkdesc(st + wg * 8192, 16, 1024, 1);
        const uint64_t db = mkdesc(st + Q_AB, 4096, 1024, 1);
        const uint64_t dr = mkdesc(st + Q_AB + 12288, 1024, 256, 3);
        if (layer == 0) {
            wg_fence();
#pragma unroll
            for (int ks = 0; ks < 4; ks++) {
                const int sc = 1;
                wgmma_n192<0, 1>(*(float(*)[96]) & acc[0], da + ks * 2, db + (ks >> 1) * 960 + (ks & 1) * 128, sc);
                wgmma_n48<0, 1>(*(float(*)[24]) & acc[96], da + ks * 2, dr + (ks >> 1) * 960 + (ks & 1) * 32, sc);
            }
            wg_commit();
        } else {
            wg_fence();
#pragma unroll
            for (int ks = 0; ks < 4; ks++) {
                const int sc = 1;
                wgmma_n192<1, 1>(*(float(*)[96]) & acc[0], da + ks * 128, db + (ks >> 1) * 960 + (ks & 1) * 128, sc);
                wgmma_n48<1, 1>(*(float(*)[24]) & acc[96], da + ks * 128, dr + (ks >> 1) * 960 + (ks & 1) * 32, sc);
            }
            wg_commit();
        }
        wg_wait<1>();
        if (it > 0) release(it - 1);
    }
    asm volatile("setmaxnreg.inc.sync.aligned.u32 %0;" ::"n"(R_CONS));
    mbar_wait(BAR(prep), 0);
    const uint32_t ob = layer ^ 1;
    const bool first = (blk == 0 && w == 0);
    const bool sel0 = (2 * q > g), sel1 = (2 * q + 1 > g);
    constexpr float SC = 0.22360679774997896f * 1.4426950408889634f;
    const float m0 = __uint_as_float(lds32(MISC(mean) + 4 * (16 * warp + g))), m1 = __uint_as_float(lds32(MISC(mean) + 4 * (16 * warp + g + 8)));
    uint4 cs[3][5];
    auto cs_load = [&](int p) {
#pragma unroll
        for (int i = 0; i < 5; i++) cs[p][i] = lds128(MISC(cs) + 4 * (80 * p + 20 * q + 4 * i));
    };
    cs_load(1); cs_load(2);
    wg_wait<0>();
    TS(7);
    if (lane == 0) mbar_arrive(BAR(qdone));
    uint32_t ql[10], qh[10], kl[10], kh[10], vl[10], vh[10];
    auto fold = [&](int p, int f, int h) {
        const int j = (f < 8) ? 8 * p + f : 24 + 2 * p + (f - 8);
        const float c0 = __uint_as_float(u4(cs[p][f >> 1], 2 * (f & 1))), c1 = __uint_as_float(u4(cs[p][f >> 1], 2 * (f & 1) + 1));
        const float m = h ? m1 : m0;
        return pack2(fmaf(-m, c0, acc[4 * j + 2 * h]), fmaf(-m, c1, acc[4 * j + 2 * h + 1]));
    };
#pragma unroll
    for (int f = 0; f < 10; f++) { vh[f] = fold(2, f, 1); if (f < A_VLO) vl[f] = fold(2, f, 0); }
#pragma unroll
    for (int f = 0; f < 10; f++) kh[f] = fold(1, f, 1);
#pragma unroll
    for (int f = 0; f < A_VLO; f++) asm volatile("" : "+r"(vl[f]));
    {
        const uint32_t mk = w == 3 ? 1u : 0u;
        auto mark = [&](uint32_t& v) { v = (v & ~mk) | (ob & mk); };
        mark(kh[0]); mark(kh[5]); mark(vh[0]); mark(vh[4]); mark(vh[8]);
    }
    if (w == 3) {
        uint4* hp = &g_halo[bx][wg][0][lane];
        st_ll4(hp, kh[0], kh[1], kh[3], kh[4]); st_ll4(hp + 32, kh[5], kh[6], kh[8], kh[9]);
        st_ll4(hp + 64, vh[0], vh[1], vh[2], vh[3]); st_ll4(hp + 96, vh[4], vh[5], vh[6], vh[7]);
        st_ll4(hp + 128, vh[8], vh[9], kh[2], kh[7]);
    } else {
        const uint32_t a = sb + Q_EOFF + wg * 8192 + w * Q_ESLOT + mj * Q_EROW + mi * 16;
        stsm_x4(a, kh[0], kh[1], kh[3], kh[4]);
        stsm_x4(a + 64, kh[5], kh[6], kh[8], kh[9]);
        stsm_x4(a + 128, vh[0], vh[1], vh[2], vh[3]);
        stsm_x4(a + 192, vh[4], vh[5], vh[6], vh[7]);
        stsm_x4(a + 256, vh[8], vh[9], kh[2], kh[7]);
        __syncwarp();
        if (lane == 0) mbar_arrive(BAR(ex) + 8 * warp);
    }
    TS(9);
    cs_load(0);
#pragma unroll
    for (int f = 0; f < 10; f++) { kl[f] = fold(1, f, 0); if (f >= A_VLO) vl[f] = fold(2, f, 0); }
#pragma unroll
    for (int f = 0; f < 10; f++) { ql[f] = fold(0, f, 0); qh[f] = fold(0, f, 1); }
    auto rs = [&](int i) { return __uint_as_float(lds32(MISC(rstd) + 4 * (72 * wg + 16 * w + i))); };
    const float kx0 = rs(2 * q + (sel0 ? 0 : 8)), kx1 = rs(2 * q + (sel1 ? 1 : 9)), ky0 = rs(2 * q + (sel0 ? 8 : 16)), ky1 = rs(2 * q + (sel1 ? 9 : 17));
    const float rx = SC * rs(8 + g), ry = SC * rs(16 + g), cx0 = rx * kx0, cx1 = rx * kx1, cy0 = ry * ky0, cy1 = ry * ky1;
    uint4 hv[5];
    const uint4* hp = &g_halo[bx - 1][wg][0][lane];
    auto prev = [&] {
        if (w > 0) {
            const uint32_t a = sb + Q_EOFF + wg * 8192 + (w - 1) * Q_ESLOT + mj * Q_EROW + mi * 16;
            mbar_wait(BAR(ex) + 8 * (warp - 1), 0);
            ldsm_x4(hv[0].x, hv[0].y, hv[0].z, hv[0].w, a);
            ldsm_x4(hv[1].x, hv[1].y, hv[1].z, hv[1].w, a + 64);
            ldsm_x4_t(hv[2].x, hv[2].y, hv[2].z, hv[2].w, a + 128);
            ldsm_x4_t(hv[3].x, hv[3].y, hv[3].z, hv[3].w, a + 192);
            ldsm_x2_t(hv[4].x, hv[4].y, a + 256);
            ldsm_x2(hv[4].z, hv[4].w, a + 288 - (lane >> 4) * 32);
        } else if (blk > 0) {
#pragma unroll
            for (int f = 0; f < 5; f++) hv[f] = ld_ll4(hp + 32 * f);
        } else {
#pragma unroll
            for (int f = 0; f < 5; f++) hv[f] = make_uint4(0, 0, 0, 0);
        }
    };
    uint32_t vt[10][2];
#pragma unroll
    for (int f = 0; f < 10; f++) { vt[f][0] = movm_t(vl[f]); vt[f][1] = movm_t(vh[f]); }
    prev();
    TS(10);
    auto FA = [](int h) { return h == 0 ? 0 : h == 1 ? 3 : h == 2 ? 5 : 8; };
    auto FH = [](int h) { return h < 2 ? 2 : 7; };
    const uint32_t pm = (sel0 ? 0xFFFFu : 0u) | (sel1 ? 0xFFFF0000u : 0u);
    auto softmax = [&](float x0, float x1, float k0, float k1) {
        float mx = fmaxf(x0, x1);
        mx = fmaxf(mx, __shfl_xor_sync(~0u, mx, 1));
        mx = fmaxf(mx, __shfl_xor_sync(~0u, mx, 2));
        x0 = ex2(x0 - mx); x1 = ex2(x1 - mx);
        float sx = x0 + x1;
        sx += __shfl_xor_sync(~0u, sx, 1);
        sx += __shfl_xor_sync(~0u, sx, 2);
        const float ix = frcp(sx);
        return pack2(x0 * k0 * ix, x1 * k1 * ix);
    };
    uint32_t qm[4][2], py[4];
    float sl[4][2];
#pragma unroll
    for (int h = 0; h < 4; h++) {
        const int fa = FA(h), fb = fa + 1, fh = FH(h);
        const bool mine = (h & 1) ? (q >= 2) : (q < 2);
        qm[h][0] = mine ? ql[fh] : 0u; qm[h][1] = mine ? qh[fh] : 0u;
        float S1[4] = {0.f, 0.f, 0.f, 0.f}, S2[4] = {0.f, 0.f, 0.f, 0.f};
        mma16816(S1, ql[fa], qh[fa], ql[fb], qh[fb], kl[fa], kl[fb]); mma1688(S1, qm[h][0], qm[h][1], kl[fh]);
        mma16816(S2, ql[fa], qh[fa], ql[fb], qh[fb], kh[fa], kh[fb]); mma1688(S2, qm[h][0], qm[h][1], kh[fh]);
        sl[h][0] = S1[0]; sl[h][1] = S1[1];
        py[h] = softmax((sel0 ? S1[2] : S2[2]) * cy0, (sel1 ? S1[3] : S2[3]) * cy1, ky0, ky1);
    }
    TS(11);
    if (w == 0 && blk > 0) {
        ll_check5(hv, hp, ob);
#pragma unroll
        for (int f = 2; f < 4; f++) hv[f] = make_uint4(movm_t(hv[f].x), movm_t(hv[f].y), movm_t(hv[f].z), movm_t(hv[f].w));
        hv[4].x = movm_t(hv[4].x); hv[4].y = movm_t(hv[4].y);
    }
    const uint32_t kp[10] = {hv[0].x, hv[0].y, hv[4].z, hv[0].z, hv[0].w, hv[1].x, hv[1].y, hv[4].w, hv[1].z, hv[1].w};
    const uint32_t vp[10] = {hv[2].x, hv[2].y, hv[2].z, hv[2].w, hv[3].x, hv[3].y, hv[3].z, hv[3].w, hv[4].x, hv[4].y};
    TS(12);
    const uint4 ko[2] = {ldg_tab(16, tid & 127), ldg_tab(17, tid & 127)};
    const float bx0 = first && sel0 ? -INFINITY : 0.f, bx1 = first && sel1 ? -INFINITY : 0.f;
    float oacc[10][4];
#pragma unroll
    for (int h = 0; h < 4; h++) {
        const int fa = FA(h), fb = fa + 1, fh = FH(h);
        const bool mine = (h & 1) ? (q >= 2) : (q < 2);
        float S0[4] = {0.f, 0.f, 0.f, 0.f};
        mma16816(S0, ql[fa], qh[fa], ql[fb], qh[fb], kp[fa], kp[fb]); mma1688(S0, qm[h][0], qm[h][1], kp[fh]);
        const uint32_t px = softmax(fmaf(sel0 ? S0[0] : sl[h][0], cx0, bx0), fmaf(sel1 ? S0[1] : sl[h][1], cx1, bx1), kx0, kx1);
#pragma unroll
        for (int i = 0; i < 3; i++) {
            const int f = (i == 0) ? fa : (i == 1) ? fb : fh;
            float O[4] = {0.f, 0.f, 0.f, 0.f};
            mma16816(O, px & ~pm, py[h] & pm, 0u, py[h] & ~pm, vt[f][0], vt[f][1]);
            mma1688(O, px & pm, 0u, vp[f]);
            if (i < 2 || !(h & 1) || mine) { oacc[f][0] = O[0]; oacc[f][1] = O[1]; oacc[f][2] = O[2]; oacc[f][3] = O[3]; }
        }
    }
    TS(13);
    float aw[40];
    uint4 of[5];
    const uint32_t fb = EPOCH ^ ob;
    {
        const uint32_t mk[2] = {q == ((2 * w) & 3), q == ((2 * w + 1) & 3)};
        uint32_t* dst = &g_of[hg][blk][640 * wg + 16 * w].x + lane;
#pragma unroll
        for (int i = 0; i < 20; i++) {
            const uint32_t v = (pack2(oacc[i >> 1][2 * (i & 1)], oacc[i >> 1][2 * (i & 1) + 1]) & ~mk[i & 1]) | (fb & mk[i & 1]);
            u4r(of[i >> 2], i & 3) = v;
            asm volatile("st.relaxed.gpu.global.u32 [%0], %1;" ::"l"(dst + 256 * (i >> 1) + 32 * (i & 1)), "r"(v) : "memory");
        }
        if (lane == 0) mbar_arrive(BAR(att) + 8 * wg);
        TS(14);
    }
    named_bar(1 + wg, 128);
    kernel_stage<2>(ko, sb + Q_KDUMP + 2 * wg * KG_RES, MISC(kg), 2 * wg, sb + F_EO + wg * 8192, w, lane);
    TS(15);
    uint32_t res[20];
    mbar_wait(BAR(res), 0);
    const uint32_t ta = (8 * (mi >> 1) + mj) * 128 + (((2 * w + (mi & 1)) ^ mj) << 4);
    if (layer == 0) {
        const int tok = 16 * w + 8 * (mi & 1) + mj;
#pragma unroll
        for (int k = 0; k < 4; k++)
            ldsm_x4(res[4 * k], res[4 * k + 1], res[4 * k + 2], res[4 * k + 3], sb + W_RES + wg * 10240 + tok * 128 + (((2 * k + (mi >> 1)) ^ mj) << 4));
        ldsm_x4(res[16], res[17], res[18], res[19], sb + W_RES + wg * 10240 + 8192 + tok * 32 + (((mi >> 1) ^ (mj >> 2)) << 4));
    } else {
#pragma unroll
        for (int k = 0; k < 5; k++) ldsm_x4_t(res[4 * k], res[4 * k + 1], res[4 * k + 2], res[4 * k + 3], sb + W_RES + wg * 10240 + k * 2048 + ta);
    }
    fence_async_smem();
    __syncwarp();
    if (lane == 0) mbar_arrive(MISC(ob) + 96 * wg + 64);
    {
#pragma unroll
        for (int i = 0; i < 20; i++) { aw[2 * i] = bf_lo(res[i]); aw[2 * i + 1] = bf_hi(res[i]); }
        mbar_wait(BAR(wfull), 0);
        const uint64_t dm = mkdesc(sb + w_grp(0), 1280, 128, 0);
        wg_fence();
#pragma unroll
        for (int k = 0; k < 5; k++) wgmma_rs80(aw, of[k], dm + k * 160, 1);
        wg_commit();
    }
    conv_tables();
    wg_wait<0>();
    TS(8);
    const uint32_t ck = mi * 1024 + (2 * w + (g & 1)) * 128 + q * 32 + (mi & 1) * 16 + ((2 * w + (g & 1)) & 3) * 4;
    uint32_t bar = MISC(ob) + 96 * wg + 8;
    uint64_t dm = mkdesc(sb + w_grp(1), 1280, 128, 0);
    const uint64_t d0 = mkdesc(sb + o_slot(wg, 0), 1024, 128, 0);
#pragma unroll 1
    for (int j = 1; j < 8; j++, bar += 8, dm += 800) {
        const uint32_t so = (j & 3) * 20480, a = sb + o_slot(wg, 0) + so + ck;
        mbar_wait(bar, layer);
        if (__any_sync(~0u, miss(miss(miss(0, lds32(a), fb), lds32(a + 4096), fb), lds32(a + 8192 - (mi & 2) * 1024), fb) & 1u)) {
            COUNT(layer);
            const uint32_t* src = &g_of[osrc_of(j)][blk][640 * wg + 16 * w].x + lane;
#pragma unroll 1
            for (int i = 0, spin = 0; i < 10;) {
                uint32_t v[4];
#pragma unroll
                for (int k = 0; k < 4; k++) asm volatile("ld.relaxed.gpu.global.u32 %0, [%1];" : "=r"(v[k]) : "l"(src + 256 * (i + (k >> 1)) + 32 * (k & 1)) : "memory");
                const int h = q ^ ((2 * w) & 3);
                if (__any_sync(~0u, h < 2 && (miss(miss(0, h ? v[1] : v[0], fb), h ? v[3] : v[2], fb) & 1u)) && ++spin < (1 << 18)) continue;
#pragma unroll
                for (int k = 0; k < 4; k++) sts32(sb + o_slot(wg, 0) + so + (i + (k >> 1)) * 1024 + (2 * w + (k & 1)) * 128 + lane * 4, v[k]);
                i += 2;
            }
            fence_async_smem();
            __syncwarp();
        }
        if (j == 1) TS(17);
        if (j == 5) TS(18);
        const uint64_t da = d0 + (so >> 4);
        wg_fence();
#pragma unroll
        for (int k = 0; k < 5; k++) wgmma_ss80(aw, da + k * 128, dm + k * 160);
        wg_commit();
        wg_wait<1>();
        if (j > 1 && j < 5 && lane == 0) mbar_arrive(bar + 56);
    }
    if (lane == 0) mbar_arrive(BAR(soon) + 8 * wg);
    named_bar(1 + wg, 128);
    wg_wait<0>();
    TS(19);
    {
        float a[2][4] = {{0.f, 0.f, 0.f, 0.f}, {0.f, 0.f, 0.f, 0.f}};
#pragma unroll
        for (int i = 0; i < 40; i++) { a[i & 1][i & 2] += aw[i]; a[i & 1][(i & 2) + 1] = fmaf(aw[i], aw[i], a[i & 1][(i & 2) + 1]); }
#pragma unroll
        for (int j = 0; j < 4; j++) { a[0][j] += a[1][j]; a[0][j] += __shfl_xor_sync(~0u, a[0][j], 1); a[0][j] += __shfl_xor_sync(~0u, a[0][j], 2); }
        if (q == 0) st_ll4(&g_sp2[blk][warp][hg][g], (__float_as_uint(a[0][0]) & ~1u) | ob, __float_as_uint(a[0][1]), __float_as_uint(a[0][2]), __float_as_uint(a[0][3]));
    }
    TS(23);
#pragma unroll
    for (int i = 0; i < 20; i++) res[i] = pack2(aw[2 * i], aw[2 * i + 1]);
    {
        const uint32_t mk = (g & 3) ? 0u : 0x00010001u;
#pragma unroll
        for (int k = 0; k < 5; k++) {
            uint32_t m[4];
#pragma unroll
            for (int i = 0; i < 4; i++) m[i] = (res[4 * k + i] & ~mk) | (mk & (0u - ob));
            stsm_x4_t(sb + w_out(wg) + k * 2048 + ta, m[0], m[1], m[2], m[3]);
        }
        fence_async_smem();
        named_bar(1 + wg, 128);
        if (w == 0 && elect_one()) {
            asm volatile("cp.async.bulk.tensor.2d.global.shared::cta.bulk_group [%0, {%2, %3}], [%1];"
                         ::"l"(TMAP(7)), "r"(sb + w_out(wg)), "r"(1024 * wg + 64 * blk), "r"(hg * 80) : "memory");
            bulk_commit();
            mbar_arrive(BAR(staged));
        }
        __syncwarp();
        TS(20);
    }
    if (layer) {
#pragma unroll
        for (int k = 0; k < 5; k++) stsm_x4_t(sb + W_RES + wg * 10240 + k * 2048 + ta, res[4 * k], res[4 * k + 1], res[4 * k + 2], res[4 * k + 3]);
    }
    TS(22);
    TS_PHASE(2 * layer + 1);
    TS(0);
    indices();
    conv_wg<2>(cta_channel(bx, 2 * (warp >> 2)), layer, sb + F_EO + (warp >> 2) * 8192, sb + (1 + 2 * (warp >> 2)) * Q_SB, sb + F_S23, MISC(kg.kexp) + 8 * (warp >> 2),
               MISC(epoch), sb, BAR(st), BAR(fdone0), warp, lane, fa1, ftw, [&] {
        if ((warp & 3) == 0 && elect_one()) {
            asm volatile("cp.async.bulk.wait_group.read 0;" ::: "memory");
            if (layer == 0) { mbar_arrive_cta(BAR(wfree), 0); mbar_arrive_cta(BAR(wfree), 1); }
        }
        __syncwarp();
        if (warp < 4) mbar_wait(BAR(staged), 0);
    }, [&] {
        if (layer == 0 && warp >= 4 && elect_one()) {
            mbar_wait(BAR(wfree), 0);
            issue_w(BAR(full) + sizeof(Bars), warp - 4, 1);
        }
        __syncwarp();
    } TS_PASS);
    __syncwarp();
    if (lane == 0) mbar_arrive(warp < 4 ? BAR(fdone0) : BAR(fdone1));
    TS(20);
    asm volatile("setmaxnreg.dec.sync.aligned.u32 168;");
    }
    named_bar(1 + (warp >> 2), 128);
    asm volatile("setmaxnreg.dec.sync.aligned.u32 %0;" ::"n"(504 - 2 * R_CONS));
    }
    indices();
    const int cq = 4 * (warp >> 1) + (lane & 3), tg = 8 * (warp & 1) + (lane >> 2);
    const uint32_t fb = ~EPOCH & 1u;
    uint2 xr[4][2];
    __syncthreads();
    if (tid < 320) {
#pragma unroll
        for (int i = 0; i < 8; i++) {
            const int ch = 4 * cq + (i >> 1);
            asm volatile("ld.shared.v2.u32 {%0, %1}, [%2];" : "=r"(xr[i >> 1][i & 1].x), "=r"(xr[i >> 1][i & 1].y)
                         : "r"(sb + W_RES + (i & 1) * 10240 + ch * 128 + (((tg >> 1) ^ (ch & 7)) << 4) + (tg & 1) * 8) : "memory");
        }
    }
    if (tid < 320) {
        const uint4* src = &g_of[hg][blk][64 * cq + tg];
        uint4 v[4];
#pragma unroll
        for (int i = 0; i < 4; i++) v[i] = make_uint4(~fb, ~fb, ~fb, ~fb);
        auto lack = [&](int i) { return miss(0, (warp & 1) ? u4(v[i], 2 * (i & 1) + 1) : u4(v[i], 2 * (i & 1)), fb); };
        int spin = 0;
        while (true) {
#pragma unroll
            for (int i = 0; i < 4; i++) if (lack(i) & 1u) v[i] = ld_ll4(src + 16 * i);
            if (!((lack(0) | lack(1) | lack(2) | lack(3)) & 1u) || ++spin >= (1 << 18)) break;
        }
        TS(21);
#pragma unroll
        for (int i = 0; i < 16; i++) asm("add.rn.bf16x2 %0, %0, %1;" : "+r"(u4r(v[i >> 2], i & 3)) : "r"((i & 1) ? xr[i >> 2][(i >> 1) & 1].y : xr[i >> 2][(i >> 1) & 1].x));
#pragma unroll
        for (int j = 0; j < 8; j++) {
            const uint32_t sel = (j & 2) ? 0x7632 : 0x5410;
            const int k = 2 * (j & 1) + (j >> 2);
            asm volatile("st.shared.v2.u32 [%0], {%1, %2};" ::"r"(sb + 2 * Q_SB + (16 * j + tg) * 160 + cq * 8),
                         "r"(__byte_perm(u4(v[0], k), u4(v[1], k), sel)), "r"(__byte_perm(u4(v[2], k), u4(v[3], k), sel)) : "memory");
        }
        fence_async_smem();
    }
    __syncthreads();
    if (warp == 0 && elect_one()) {
        asm volatile("cp.async.bulk.tensor.3d.global.shared::cta.bulk_group [%0, {%2, %3, 0}], [%1];" ::"l"(TMAP(9)), "r"(sb + 2 * Q_SB), "r"(80 * hg), "r"(16 * blk) : "memory");
        bulk_commit();
        asm volatile("cp.async.bulk.wait_group.read 0;" ::: "memory");
    }
    if (bx == 0 && tid == 0) g_epoch = (EPOCH + 1) & 0x3FFFFFFFu;
    TS(22);
    TS_END;
}
typedef CUresult (*EncodeTiledFn)(CUtensorMap*, CUtensorMapDataType, cuuint32_t, void*, const cuuint64_t*, const cuuint64_t*, const cuuint32_t*,
                                  const cuuint32_t*, CUtensorMapInterleave, CUtensorMapSwizzle, CUtensorMapL2promotion, CUtensorMapFloatOOBfill);

static void make_map(EncodeTiledFn enc, CUtensorMap* m, const void* base, int rank, const cuuint64_t* dims, const cuuint64_t* strides,
                     const cuuint32_t* box, CUtensorMapSwizzle sw) {
    cuuint32_t es[4] = {1, 1, 1, 1};
    enc(m, CU_TENSOR_MAP_DATA_TYPE_BFLOAT16, rank, (void*)base, dims, strides, box, es, CU_TENSOR_MAP_INTERLEAVE_NONE, sw,
        sw == CU_TENSOR_MAP_SWIZZLE_128B ? CU_TENSOR_MAP_L2_PROMOTION_L2_128B : CU_TENSOR_MAP_L2_PROMOTION_NONE, CU_TENSOR_MAP_FLOAT_OOB_FILL_NONE);
}

template <typename... KArgs, typename... Args>
static void launch(void (*kern)(KArgs...), int grid, int block, int smem, int cluster, bool pdl, Args... args) {
    cudaLaunchConfig_t cfg = {};
    cfg.gridDim = dim3(grid); cfg.blockDim = dim3(block); cfg.dynamicSmemBytes = smem; cfg.stream = cudaStreamPerThread;
    cudaLaunchAttribute at[2];
    int n = 0;
    if (cluster > 1) { at[n].id = cudaLaunchAttributeClusterDimension; at[n].val.clusterDim.x = cluster; at[n].val.clusterDim.y = 1; at[n].val.clusterDim.z = 1; n++; }
    if (pdl) { at[n].id = cudaLaunchAttributeProgrammaticStreamSerialization; at[n].val.programmaticStreamSerializationAllowed = 1; n++; }
    cfg.attrs = at; cfg.numAttrs = n;
    cudaLaunchKernelEx(&cfg, kern, KArgs(args)...);
}

struct HostState {
    bool ready = false;
    const void* key[4] = {nullptr, nullptr, nullptr, nullptr};
    CUtensorMap mX[2], mRes[2], mW, mWr, mWo, mOut, mFin, mResA;
    bf16 *x1T, *x2T;
    unsigned* epoch;
};

extern "C" void kernel_launch(void* const* d_in, const int* in_sizes, int n_in, void* d_out, int out_size) {
    const bf16* x = (const bf16*)d_in[0];
    const bf16* wqkv = (const bf16*)d_in[1];
    const bf16* wo = (const bf16*)d_in[2];
    const bf16* lar = (const bf16*)d_in[4];
    const bf16* aim = (const bf16*)d_in[5];
    const bf16* cre = (const bf16*)d_in[6];
    const bf16* cim = (const bf16*)d_in[7];
    const bf16* logdt = (const bf16*)d_in[8];
    const bf16* dskip = (const bf16*)d_in[9];
    static HostState hs;
    if (!hs.ready || hs.key[0] != wqkv || hs.key[1] != wo || hs.key[2] != x || hs.key[3] != d_out) {
        void* fn = nullptr;
        cudaDriverEntryPointQueryResult qr;
        cudaGetDriverEntryPoint("cuTensorMapEncodeTiled", &fn, cudaEnableDefault, &qr);
        EncodeTiledFn enc = (EncodeTiledFn)fn;
        cudaGetSymbolAddress((void**)&hs.epoch, g_epoch);
        cudaGetSymbolAddress((void**)&hs.x1T, g_x1T);
        cudaGetSymbolAddress((void**)&hs.x2T, g_x2T);
        {
            cuuint64_t d[3] = {DM, SEQ / 2, 2}, s[2] = {DM * 4, DM * 2};
            cuuint32_t b[3] = {64, 64, 2}, ba[3] = {64, 64, 1}, br[3] = {16, 64, 1};
            make_map(enc, &hs.mX[0], x, 3, d, s, b, CU_TENSOR_MAP_SWIZZLE_128B);
            make_map(enc, &hs.mResA, x, 3, d, s, ba, CU_TENSOR_MAP_SWIZZLE_128B);
            make_map(enc, &hs.mRes[0], x, 3, d, s, br, CU_TENSOR_MAP_SWIZZLE_32B);
            cuuint64_t d2[3] = {SEQ / 2, DM, 2}, s2[2] = {XP * 2, SEQ};
            cuuint32_t b2[3] = {64, 80, 2};
            make_map(enc, &hs.mX[1], hs.x2T, 3, d2, s2, b, CU_TENSOR_MAP_SWIZZLE_128B);
            make_map(enc, &hs.mRes[1], hs.x2T, 3, d2, s2, b2, CU_TENSOR_MAP_SWIZZLE_128B);
            cuuint64_t d3[2] = {SEQ, DM};
            make_map(enc, &hs.mOut, hs.x1T, 2, d3, s2, b2, CU_TENSOR_MAP_SWIZZLE_128B);
        }
        { cuuint64_t d[2] = {3 * DM, DM}, s[1] = {3 * DM * 2}; cuuint32_t b[2] = {64, 32};
          make_map(enc, &hs.mW, wqkv, 2, d, s, b, CU_TENSOR_MAP_SWIZZLE_128B); }
        { cuuint64_t d[3] = {DM, DM, 3}, s[2] = {3 * DM * 2, DM * 2}; cuuint32_t b[3] = {16, 32, 3};
          make_map(enc, &hs.mWr, wqkv, 3, d, s, b, CU_TENSOR_MAP_SWIZZLE_32B); }
        { cuuint64_t d[4] = {8, 8, DM / 8, DM / 8}, s[3] = {DM * 2, 16, DM * 16}; cuuint32_t b[4] = {8, 8, 10, 5};
          make_map(enc, &hs.mWo, wo, 4, d, s, b, CU_TENSOR_MAP_SWIZZLE_NONE); }
        { cuuint64_t d[3] = {DM, SEQ / 8, 8}, s[2] = {DM * 16, DM * 2}; cuuint32_t b[3] = {80, 16, 8};
          make_map(enc, &hs.mFin, d_out, 3, d, s, b, CU_TENSOR_MAP_SWIZZLE_NONE); }
        cudaFuncSetAttribute(fused_kernel, cudaFuncAttributeMaxDynamicSharedMemorySize, Q_SMEM);
        hs.key[0] = wqkv; hs.key[1] = wo; hs.key[2] = x; hs.key[3] = d_out;
        hs.ready = true;
    }
    const SsmParams sp = {lar, aim, cre, cim, logdt, dskip, hs.epoch};
    launch(fused_kernel, 128, 384, Q_SMEM, 2, false, sp, hs.mX[0], hs.mX[1], hs.mW, hs.mWr, hs.mRes[0], hs.mRes[1], hs.mOut, hs.mWo, hs.mFin, hs.mResA);
}
```
